```python
import torch

def _softmax(x, axis=-1):
    return torch.softmax(x, dim=axis)
def _gelu(x):
    return torch.nn.functional.gelu(x, approximate="tanh")
def _silu(x):
    return torch.nn.functional.silu(x)
def _sigmoid(x):
    return torch.sigmoid(x)
def _layernorm(x, axis=-1, eps=1e-5):
    m = x.mean(dim=axis, keepdim=True)
    v = x.var(dim=axis, keepdim=True, unbiased=False)
    return (x - m) / torch.sqrt(v + eps)
def _scatter_add(tgt, idx, src, axis=0):
    return tgt.clone().index_add_(axis, idx, src)
def _segment_sum(src, seg, n):
    out = torch.zeros((n,) + src.shape[1:], dtype=src.dtype)
    return out.index_add_(0, seg, src)
def _pad(x, pw):
    flat = tuple(v for pair in reversed(pw) for v in pair)
    return torch.nn.functional.pad(x, flat)

kernel_name = 'concat_heads__spectral_gfnet__ssm_conv_s5__prompt'

def setup_inputs():

    _w = (lambda a: (lambda t: t.to(torch.bfloat16) if t.is_floating_point() else t)(torch.as_tensor(a)))
    def _A_setup():
        B, S, D = 1, 2048, 1024
        Df = D // 2 + 1
        return {
            "x": _w((lambda *s: torch.randn(*s, dtype=torch.bfloat16) * 0.05)(B, S, D)),
            "w_r": _w((lambda *s: torch.randn(*s, dtype=torch.bfloat16) * 0.8)(S, Df) * 0.02),
            "w_i": _w((lambda *s: torch.randn(*s, dtype=torch.bfloat16) * 0.8)(S, Df) * 0.02),
        }
    _A_in = _A_setup()

    def _B_setup():
        B, S, D = 1, 2048, 1024
        P = D
        Lambda_re = -0.5 * (lambda _x: torch.exp(torch.as_tensor(_x)))((lambda *s: torch.randn(*s, dtype=torch.bfloat16) * 0.2)(P))
        Lambda_im = (lambda *s: torch.randn(*s, dtype=torch.bfloat16) * 0.4)(P) * 1.0
        B_re = (lambda *s: torch.randn(*s, dtype=torch.bfloat16) * 0.2)(P, D) * (D ** -0.5)
        B_im = (lambda *s: torch.randn(*s, dtype=torch.bfloat16) * 0.2)(P, D) * (D ** -0.5)
        C_re = (lambda *s: torch.randn(*s, dtype=torch.bfloat16) * 0.2)(D, P) * (P ** -0.5)
        C_im = (lambda *s: torch.randn(*s, dtype=torch.bfloat16) * 0.2)(D, P) * (P ** -0.5)
        log_dt = (lambda *s: torch.randn(*s, dtype=torch.bfloat16) * 0.2)(P) * 0.3 - 2.0
        Dskip = (lambda *s: torch.randn(*s, dtype=torch.bfloat16) * 0.05)(D)
        return {
            "x": _w((lambda *s: torch.randn(*s, dtype=torch.bfloat16) * 0.05)(B, S, D)),
            "Lambda_re": _w(Lambda_re),
            "Lambda_im": _w(Lambda_im),
            "B_re": _w(B_re),
            "B_im": _w(B_im),
            "C_re": _w(C_re),
            "C_im": _w(C_im),
            "log_dt": _w(log_dt),
            "Dskip": _w(Dskip),
        }
    _B_in = _B_setup()

    return {
        "A_x": _A_in["x"],
        "A_w_r": _A_in["w_r"],
        "A_w_i": _A_in["w_i"],
        "B_x": _B_in["x"],
        "B_Lambda_re": _B_in["Lambda_re"],
        "B_Lambda_im": _B_in["Lambda_im"],
        "B_B_re": _B_in["B_re"],
        "B_B_im": _B_in["B_im"],
        "B_C_re": _B_in["C_re"],
        "B_C_im": _B_in["C_im"],
        "B_log_dt": _B_in["log_dt"],
        "B_Dskip": _B_in["Dskip"],
    }

def reference(A_x, A_w_r, A_w_i, B_x, B_Lambda_re, B_Lambda_im, B_B_re, B_B_im, B_C_re, B_C_im, B_log_dt, B_Dskip):
    def _A_ref(x, w_r, w_i):
        B, S, D = x.shape
        X = (lambda x, axes=(-2,-1): torch.fft.rfft2(x.float(), dim=axes))(x, axes=(-2, -1))
        W = w_r + 1j * w_i
        X = X * W
        y = (lambda x, s, axes=(-2,-1): torch.fft.irfft2(x, s=s, dim=axes).to(torch.bfloat16))(X, (S, D), axes=(-2, -1))
        return y

    def _B_ref(x, Lambda_re, Lambda_im, B_re, B_im, C_re, C_im, log_dt, Dskip):
        Bsz, L, H = x.shape
        Lam = Lambda_re + 1j * Lambda_im
        Bmat = B_re + 1j * B_im
        Cmat = C_re + 1j * C_im
        dt = torch.exp(log_dt)
        Lam_bar = torch.exp(dt * Lam)
        B_bar = ((Lam_bar - 1.0) / Lam)[:, None] * Bmat
        Bu = torch.einsum("bld,pd->blp", x + 0j, B_bar)
        h = torch.zeros_like(Bu[:, 0, :])
        hs = []
        for t in range(L):
            h = Lam_bar[None, :] * h + Bu[:, t, :]
            hs.append(h)
        hseq = torch.stack(hs, 1)
        y = 2.0 * torch.einsum("blp,dp->bld", hseq, Cmat).real + x * Dskip[None, None, :]
        return y

    a = _A_ref(A_x, A_w_r, A_w_i)
    b = _B_ref(B_x, B_Lambda_re, B_Lambda_im, B_B_re, B_B_im, B_C_re, B_C_im, B_log_dt, B_Dskip)
    return torch.concatenate([a, b], axis=-1)
```

```cpp
#include <cuda_runtime.h>
#include <cuda.h>
#include <cuda_bf16.h>
#include <stdint.h>

#define NST 5
#define OFF_P (NST * 32768)
#define OFF_F (OFF_P + 32768)
#define OFF_X (OFF_F + 8192)
#define OFF_Q (OFF_X + 8448)
#define OFF_BAR (OFF_Q + 16384)
#define OFF_LAM (OFF_BAR + 320)
#define OFF_WSP (OFF_LAM + 2048)
#define SMEM_BYTES (OFF_WSP + 128)
#define WPITCH 1056
#define B_FULL 0
#define B_EMPTY 48
#define B_HRDY 96
#define B_EP 128
#define B_LAM 136
#define B_STG 144
#define B_QFREE 152
#define B_LDONE 160
#define B_FG 168
#define B_UIN 176
#define B_STGU 192
#define B_WSP 200
#define B_WFREE 208
#define B_HOWN 216
#define B_WD 248
#define B_WM 256
#define B_XIN 264
#define B_QRD 304
#define B_VIN 280
#define B_EPOCH 296

#define PACE_U 20
#define PACE_V 20
#define PACE_O 150
#define LDK 61
#define UBOX 32
#define VBOX 64
#define SKEW 2
#define QFREE_N 8
#define SPIN_LIMIT (1u << 15)

__device__ __align__(1024) uint8_t g_U[4 << 20];
__device__ __align__(1024) uint8_t g_V[4 << 20];
__device__ __align__(1024) uint8_t g_H[8 << 20];
__device__ __align__(1024) uint4 g_carry[16 * 512];
__device__ __align__(1024) unsigned g_hcnt[16 * 32];
__device__ __align__(128) unsigned g_cnt[64];
__device__ __align__(128) unsigned g_epoch[129 * 8];

#define STAMP(i) do { } while (0)
#define STAMPR(i) do { } while (0)
#define STAMPW(a, b) do { } while (0)
#define STAMPX(a, b) do { } while (0)
#define STAMP3(i) do { } while (0)

#define TAB_FG 0
#define TAB_F1 2048
#define TAB_T 4096
#define TAB_SP 6144
#define TAB_TW 7168
#define TAB_FX 7680
__device__ __align__(1024) const uint32_t g_tab[7808] = {
0x80003d80,0x80003d80,0x80003d80,0x80003d80,0x80003d80,0x80003d80,0x80003d80,0x80003d80,0x80003d80,0x80003d80,0x80003d80,0x80003d80,0x80003d80,0x80003d80,0x80003d80,0x80003d80,
0x80003d80,0x80003d80,0x80003d80,0x80003d80,0x80003d80,0x80003d80,0x80003d80,0x80003d80,0x80003d80,0x80003d80,0x80003d80,0x80003d80,0x80003d80,0x80003d80,0x80003d80,0x80003d80,
0x3c483d7b,0x3d0e3d55,0x3d553d0e,0x3d7b3c48,0x80003d80,0x3cc43d6d,0x3d353d35,0x3d6d3cc4,0x3d7bbc48,0x3d55bd0e,0x3d0ebd55,0x3c48bd7b,0x3d800000,0x3d6dbcc4,0x3d35bd35,0x3cc4bd6d,
0xbc48bd7b,0xbd0ebd55,0xbd55bd0e,0xbd7bbc48,0x8000bd80,0xbcc4bd6d,0xbd35bd35,0xbd6dbcc4,0xbd7b3c48,0xbd553d0e,0xbd0e3d55,0xbc483d7b,0xbd800000,0xbd6d3cc4,0xbd353d35,0xbcc43d6d,
0x8000bd80,0xbd35bd35,0xbd800000,0xbd353d35,0xbcc4bd6d,0xbd6dbcc4,0xbd6d3cc4,0xbcc43d6d,0x80003d80,0x3d353d35,0x3d800000,0x3d35bd35,0x3cc43d6d,0x3d6d3cc4,0x3d6dbcc4,0x3cc4bd6d,
0x8000bd80,0xbd35bd35,0xbd800000,0xbd353d35,0xbcc4bd6d,0xbd6dbcc4,0xbd6d3cc4,0xbcc43d6d,0x80003d80,0x3d353d35,0x3d800000,0x3d35bd35,0x3cc43d6d,0x3d6d3cc4,0x3d6dbcc4,0x3cc4bd6d,
0xbd553d0e,0x3c483d7b,0x3d7b3c48,0x3d0ebd55,0xbd800000,0xbcc43d6d,0x3d353d35,0x3d6dbcc4,0x3d0e3d55,0x3d7bbc48,0x3c48bd7b,0xbd55bd0e,0x80003d80,0x3d6d3cc4,0x3d35bd35,0xbcc4bd6d,
0x3d55bd0e,0xbc48bd7b,0xbd7bbc48,0xbd0e3d55,0x3d800000,0x3cc4bd6d,0xbd35bd35,0xbd6d3cc4,0xbd0ebd55,0xbd7b3c48,0xbc483d7b,0x3d553d0e,0x8000bd80,0xbd6dbcc4,0xbd353d35,0x3cc43d6d,
0x80003d80,0x3d800000,0x8000bd80,0xbd800000,0x3d353d35,0x3d35bd35,0xbd35bd35,0xbd353d35,0x80003d80,0x3d800000,0x8000bd80,0xbd800000,0x3d353d35,0x3d35bd35,0xbd35bd35,0xbd353d35,
0x80003d80,0x3d800000,0x8000bd80,0xbd800000,0x3d353d35,0x3d35bd35,0xbd35bd35,0xbd353d35,0x80003d80,0x3d800000,0x8000bd80,0xbd800000,0x3d353d35,0x3d35bd35,0xbd35bd35,0xbd353d35,
0xbd55bd0e,0xbc483d7b,0x3d7bbc48,0xbd0ebd55,0x8000bd80,0xbd6d3cc4,0x3d353d35,0x3cc4bd6d,0xbd0e3d55,0x3d7b3c48,0xbc48bd7b,0xbd553d0e,0xbd800000,0x3cc43d6d,0x3d35bd35,0xbd6dbcc4,
0x3d553d0e,0x3c48bd7b,0xbd7b3c48,0x3d0e3d55,0x80003d80,0x3d6dbcc4,0xbd35bd35,0xbcc43d6d,0x3d0ebd55,0xbd7bbc48,0x3c483d7b,0x3d55bd0e,0x3d800000,0xbcc4bd6d,0xbd353d35,0x3d6d3cc4,
0x8000bd80,0xbd353d35,0x3d800000,0xbd35bd35,0xbd6dbcc4,0x3cc43d6d,0x3cc4bd6d,0xbd6d3cc4,0x80003d80,0x3d35bd35,0xbd800000,0x3d353d35,0x3d6d3cc4,0xbcc4bd6d,0xbcc43d6d,0x3d6dbcc4,
0x8000bd80,0xbd353d35,0x3d800000,0xbd35bd35,0xbd6dbcc4,0x3cc43d6d,0x3cc4bd6d,0xbd6d3cc4,0x80003d80,0x3d35bd35,0xbd800000,0x3d353d35,0x3d6d3cc4,0xbcc4bd6d,0xbcc43d6d,0x3d6dbcc4,
0x3c48bd7b,0xbd0e3d55,0x3d55bd0e,0xbd7b3c48,0x3d800000,0xbd6dbcc4,0x3d353d35,0xbcc4bd6d,0xbd7bbc48,0x3d553d0e,0xbd0ebd55,0x3c483d7b,0x8000bd80,0xbcc43d6d,0x3d35bd35,0xbd6d3cc4,
0xbc483d7b,0x3d0ebd55,0xbd553d0e,0x3d7bbc48,0xbd800000,0x3d6d3cc4,0xbd35bd35,0x3cc43d6d,0x3d7b3c48,0xbd55bd0e,0x3d0e3d55,0xbc48bd7b,0x80003d80,0x3cc4bd6d,0xbd353d35,0x3d6dbcc4,
0x3d800000,0x3d800000,0x3d800000,0x3d800000,0x3d800000,0x3d800000,0x3d800000,0x3d800000,0x3d800000,0x3d800000,0x3d800000,0x3d800000,0x3d800000,0x3d800000,0x3d800000,0x3d800000,
0x3d800000,0x3d800000,0x3d800000,0x3d800000,0x3d800000,0x3d800000,0x3d800000,0x3d800000,0x3d800000,0x3d800000,0x3d800000,0x3d800000,0x3d800000,0x3d800000,0x3d800000,0x3d800000,
0x3d7bbc48,0x3d55bd0e,0x3d0ebd55,0x3c48bd7b,0x3d800000,0x3d6dbcc4,0x3d35bd35,0x3cc4bd6d,0xbc48bd7b,0xbd0ebd55,0xbd55bd0e,0xbd7bbc48,0xbd80,0xbcc4bd6d,0xbd35bd35,0xbd6dbcc4,
0xbd7b3c48,0xbd553d0e,0xbd0e3d55,0xbc483d7b,0xbd800000,0xbd6d3cc4,0xbd353d35,0xbcc43d6d,0x3c483d7b,0x3d0e3d55,0x3d553d0e,0x3d7b3c48,0x3d80,0x3cc43d6d,0x3d353d35,0x3d6d3cc4,
0xbd800000,0xbd353d35,0x3d80,0x3d353d35,0xbd6d3cc4,0xbcc43d6d,0x3cc43d6d,0x3d6d3cc4,0x3d800000,0x3d35bd35,0xbd80,0xbd35bd35,0x3d6dbcc4,0x3cc4bd6d,0xbcc4bd6d,0xbd6dbcc4,
0xbd800000,0xbd353d35,0x3d80,0x3d353d35,0xbd6d3cc4,0xbcc43d6d,0x3cc43d6d,0x3d6d3cc4,0x3d800000,0x3d35bd35,0xbd80,0xbd35bd35,0x3d6dbcc4,0x3cc4bd6d,0xbcc4bd6d,0xbd6dbcc4,
0x3d0e3d55,0x3d7bbc48,0x3c48bd7b,0xbd55bd0e,0x3d80,0x3d6d3cc4,0x3d35bd35,0xbcc4bd6d,0x3d55bd0e,0xbc48bd7b,0xbd7bbc48,0xbd0e3d55,0x3d800000,0x3cc4bd6d,0xbd35bd35,0xbd6d3cc4,
0xbd0ebd55,0xbd7b3c48,0xbc483d7b,0x3d553d0e,0xbd80,0xbd6dbcc4,0xbd353d35,0x3cc43d6d,0xbd553d0e,0x3c483d7b,0x3d7b3c48,0x3d0ebd55,0xbd800000,0xbcc43d6d,0x3d353d35,0x3d6dbcc4,
0x3d800000,0xbd80,0xbd800000,0x3d80,0x3d35bd35,0xbd35bd35,0xbd353d35,0x3d353d35,0x3d800000,0xbd80,0xbd800000,0x3d80,0x3d35bd35,0xbd35bd35,0xbd353d35,0x3d353d35,
0x3d800000,0xbd80,0xbd800000,0x3d80,0x3d35bd35,0xbd35bd35,0xbd353d35,0x3d353d35,0x3d800000,0xbd80,0xbd800000,0x3d80,0x3d35bd35,0xbd35bd35,0xbd353d35,0x3d353d35,
0xbd0e3d55,0x3d7b3c48,0xbc48bd7b,0xbd553d0e,0xbd800000,0x3cc43d6d,0x3d35bd35,0xbd6dbcc4,0x3d553d0e,0x3c48bd7b,0xbd7b3c48,0x3d0e3d55,0x3d80,0x3d6dbcc4,0xbd35bd35,0xbcc43d6d,
0x3d0ebd55,0xbd7bbc48,0x3c483d7b,0x3d55bd0e,0x3d800000,0xbcc4bd6d,0xbd353d35,0x3d6d3cc4,0xbd55bd0e,0xbc483d7b,0x3d7bbc48,0xbd0ebd55,0xbd80,0xbd6d3cc4,0x3d353d35,0x3cc4bd6d,
0xbd800000,0x3d353d35,0xbd80,0xbd353d35,0xbcc43d6d,0x3d6dbcc4,0xbd6dbcc4,0x3cc43d6d,0x3d800000,0xbd35bd35,0x3d80,0x3d35bd35,0x3cc4bd6d,0xbd6d3cc4,0x3d6d3cc4,0xbcc4bd6d,
0xbd800000,0x3d353d35,0xbd80,0xbd353d35,0xbcc43d6d,0x3d6dbcc4,0xbd6dbcc4,0x3cc43d6d,0x3d800000,0xbd35bd35,0x3d80,0x3d35bd35,0x3cc4bd6d,0xbd6d3cc4,0x3d6d3cc4,0xbcc4bd6d,
0xbd7bbc48,0x3d553d0e,0xbd0ebd55,0x3c483d7b,0xbd80,0xbcc43d6d,0x3d35bd35,0xbd6d3cc4,0xbc483d7b,0x3d0ebd55,0xbd553d0e,0x3d7bbc48,0xbd800000,0x3d6d3cc4,0xbd35bd35,0x3cc43d6d,
0x3d7b3c48,0xbd55bd0e,0x3d0e3d55,0xbc48bd7b,0x3d80,0x3cc4bd6d,0xbd353d35,0x3d6dbcc4,0x3c48bd7b,0xbd0e3d55,0x3d55bd0e,0xbd7b3c48,0x3d800000,0xbd6dbcc4,0x3d353d35,0xbcc4bd6d,
0x80003d80,0x8000bd80,0x80003d80,0x8000bd80,0x3d800000,0xbd800000,0x3d800000,0xbd800000,0x80003d80,0x8000bd80,0x80003d80,0x8000bd80,0x3d800000,0xbd800000,0x3d800000,0xbd800000,
0x80003d80,0x8000bd80,0x80003d80,0x8000bd80,0x3d800000,0xbd800000,0x3d800000,0xbd800000,0x80003d80,0x8000bd80,0x80003d80,0x8000bd80,0x3d800000,0xbd800000,0x3d800000,0xbd800000,
0x3d7bbc48,0xbd553d0e,0x3d0ebd55,0xbc483d7b,0x80003d80,0xbcc4bd6d,0x3d353d35,0xbd6dbcc4,0xbc48bd7b,0x3d0e3d55,0xbd55bd0e,0x3d7b3c48,0x3d800000,0xbd6d3cc4,0x3d35bd35,0xbcc43d6d,
0xbd7b3c48,0x3d55bd0e,0xbd0e3d55,0x3c48bd7b,0x8000bd80,0x3cc43d6d,0xbd35bd35,0x3d6d3cc4,0x3c483d7b,0xbd0ebd55,0x3d553d0e,0xbd7bbc48,0xbd800000,0x3d6dbcc4,0xbd353d35,0x3cc4bd6d,
0x8000bd80,0x3d353d35,0xbd800000,0x3d35bd35,0xbd6d3cc4,0x3cc4bd6d,0x3cc43d6d,0xbd6dbcc4,0x80003d80,0xbd35bd35,0x3d800000,0xbd353d35,0x3d6dbcc4,0xbcc43d6d,0xbcc4bd6d,0x3d6d3cc4,
0x8000bd80,0x3d353d35,0xbd800000,0x3d35bd35,0xbd6d3cc4,0x3cc4bd6d,0x3cc43d6d,0xbd6dbcc4,0x80003d80,0xbd35bd35,0x3d800000,0xbd353d35,0x3d6dbcc4,0xbcc43d6d,0xbcc4bd6d,0x3d6d3cc4,
0x3d0e3d55,0xbd7b3c48,0x3c48bd7b,0x3d553d0e,0xbd800000,0x3cc4bd6d,0x3d353d35,0xbd6d3cc4,0x3d55bd0e,0x3c483d7b,0xbd7bbc48,0x3d0ebd55,0x80003d80,0xbd6dbcc4,0x3d35bd35,0x3cc43d6d,
0xbd0ebd55,0x3d7bbc48,0xbc483d7b,0xbd55bd0e,0x3d800000,0xbcc43d6d,0xbd35bd35,0x3d6dbcc4,0xbd553d0e,0xbc48bd7b,0x3d7b3c48,0xbd0e3d55,0x8000bd80,0x3d6d3cc4,0xbd353d35,0xbcc4bd6d,
0x80003d80,0xbd800000,0x8000bd80,0x3d800000,0x3d35bd35,0x3d353d35,0xbd353d35,0xbd35bd35,0x80003d80,0xbd800000,0x8000bd80,0x3d800000,0x3d35bd35,0x3d353d35,0xbd353d35,0xbd35bd35,
0x80003d80,0xbd800000,0x8000bd80,0x3d800000,0x3d35bd35,0x3d353d35,0xbd353d35,0xbd35bd35,0x80003d80,0xbd800000,0x8000bd80,0x3d800000,0x3d35bd35,0x3d353d35,0xbd353d35,0xbd35bd35,
0xbd0e3d55,0xbd7bbc48,0xbc48bd7b,0x3d55bd0e,0x8000bd80,0x3d6dbcc4,0x3d353d35,0xbcc43d6d,0x3d553d0e,0xbc483d7b,0xbd7b3c48,0xbd0ebd55,0xbd800000,0xbcc4bd6d,0x3d35bd35,0x3d6d3cc4,
0x3d0ebd55,0x3d7b3c48,0x3c483d7b,0xbd553d0e,0x80003d80,0xbd6d3cc4,0xbd35bd35,0x3cc4bd6d,0xbd55bd0e,0x3c48bd7b,0x3d7bbc48,0x3d0e3d55,0x3d800000,0x3cc43d6d,0xbd353d35,0xbd6dbcc4,
0x8000bd80,0x3d35bd35,0x3d800000,0x3d353d35,0xbcc43d6d,0xbd6d3cc4,0xbd6dbcc4,0xbcc4bd6d,0x80003d80,0xbd353d35,0xbd800000,0xbd35bd35,0x3cc4bd6d,0x3d6dbcc4,0x3d6d3cc4,0x3cc43d6d,
0x8000bd80,0x3d35bd35,0x3d800000,0x3d353d35,0xbcc43d6d,0xbd6d3cc4,0xbd6dbcc4,0xbcc4bd6d,0x80003d80,0xbd353d35,0xbd800000,0xbd35bd35,0x3cc4bd6d,0x3d6dbcc4,0x3d6d3cc4,0x3cc43d6d,
0xbd7bbc48,0xbd55bd0e,0xbd0ebd55,0xbc48bd7b,0x3d800000,0x3d6d3cc4,0x3d353d35,0x3cc43d6d,0xbc483d7b,0xbd0e3d55,0xbd553d0e,0xbd7b3c48,0x8000bd80,0x3cc4bd6d,0x3d35bd35,0x3d6dbcc4,
0x3d7b3c48,0x3d553d0e,0x3d0e3d55,0x3c483d7b,0xbd800000,0xbd6dbcc4,0xbd35bd35,0xbcc4bd6d,0x3c48bd7b,0x3d0ebd55,0x3d55bd0e,0x3d7bbc48,0x80003d80,0xbcc43d6d,0xbd353d35,0xbd6d3cc4,
0x3d800000,0xbd800000,0x3d800000,0xbd800000,0xbd80,0x3d80,0xbd80,0x3d80,0x3d800000,0xbd800000,0x3d800000,0xbd800000,0xbd80,0x3d80,0xbd80,0x3d80,
0x3d800000,0xbd800000,0x3d800000,0xbd800000,0xbd80,0x3d80,0xbd80,0x3d80,0x3d800000,0xbd800000,0x3d800000,0xbd800000,0xbd80,0x3d80,0xbd80,0x3d80,
0xbc48bd7b,0x3d0e3d55,0xbd55bd0e,0x3d7b3c48,0x3d800000,0xbd6d3cc4,0x3d35bd35,0xbcc43d6d,0xbd7b3c48,0x3d55bd0e,0xbd0e3d55,0x3c48bd7b,0xbd80,0x3cc43d6d,0xbd35bd35,0x3d6d3cc4,
0x3c483d7b,0xbd0ebd55,0x3d553d0e,0xbd7bbc48,0xbd800000,0x3d6dbcc4,0xbd353d35,0x3cc4bd6d,0x3d7bbc48,0xbd553d0e,0x3d0ebd55,0xbc483d7b,0x3d80,0xbcc4bd6d,0x3d353d35,0xbd6dbcc4,
0xbd800000,0x3d35bd35,0x3d80,0xbd35bd35,0x3cc43d6d,0xbd6dbcc4,0x3d6dbcc4,0xbcc43d6d,0x3d800000,0xbd353d35,0xbd80,0x3d353d35,0xbcc4bd6d,0x3d6d3cc4,0xbd6d3cc4,0x3cc4bd6d,
0xbd800000,0x3d35bd35,0x3d80,0xbd35bd35,0x3cc43d6d,0xbd6dbcc4,0x3d6dbcc4,0xbcc43d6d,0x3d800000,0xbd353d35,0xbd80,0x3d353d35,0xbcc4bd6d,0x3d6d3cc4,0xbd6d3cc4,0x3cc4bd6d,
0x3d55bd0e,0x3c483d7b,0xbd7bbc48,0x3d0ebd55,0x3d80,0xbd6dbcc4,0x3d35bd35,0x3cc43d6d,0xbd0ebd55,0x3d7bbc48,0xbc483d7b,0xbd55bd0e,0x3d800000,0xbcc43d6d,0xbd35bd35,0x3d6dbcc4,
0xbd553d0e,0xbc48bd7b,0x3d7b3c48,0xbd0e3d55,0xbd80,0x3d6d3cc4,0xbd353d35,0xbcc4bd6d,0x3d0e3d55,0xbd7b3c48,0x3c48bd7b,0x3d553d0e,0xbd800000,0x3cc4bd6d,0x3d353d35,0xbd6d3cc4,
0x3d800000,0x3d80,0xbd800000,0xbd80,0xbd35bd35,0x3d35bd35,0x3d353d35,0xbd353d35,0x3d800000,0x3d80,0xbd800000,0xbd80,0xbd35bd35,0x3d35bd35,0x3d353d35,0xbd353d35,
0x3d800000,0x3d80,0xbd800000,0xbd80,0xbd35bd35,0x3d35bd35,0x3d353d35,0xbd353d35,0x3d800000,0x3d80,0xbd800000,0xbd80,0xbd35bd35,0x3d35bd35,0x3d353d35,0xbd353d35,
0x3d553d0e,0xbc483d7b,0xbd7b3c48,0xbd0ebd55,0xbd800000,0xbcc4bd6d,0x3d35bd35,0x3d6d3cc4,0x3d0ebd55,0x3d7b3c48,0x3c483d7b,0xbd553d0e,0x3d80,0xbd6d3cc4,0xbd35bd35,0x3cc4bd6d,
0xbd55bd0e,0x3c48bd7b,0x3d7bbc48,0x3d0e3d55,0x3d800000,0x3cc43d6d,0xbd353d35,0xbd6dbcc4,0xbd0e3d55,0xbd7bbc48,0xbc48bd7b,0x3d55bd0e,0xbd80,0x3d6dbcc4,0x3d353d35,0xbcc43d6d,
0xbd800000,0xbd35bd35,0xbd80,0x3d35bd35,0x3d6d3cc4,0x3cc43d6d,0xbcc43d6d,0xbd6d3cc4,0x3d800000,0x3d353d35,0x3d80,0xbd353d35,0xbd6dbcc4,0xbcc4bd6d,0x3cc4bd6d,0x3d6dbcc4,
0xbd800000,0xbd35bd35,0xbd80,0x3d35bd35,0x3d6d3cc4,0x3cc43d6d,0xbcc43d6d,0xbd6d3cc4,0x3d800000,0x3d353d35,0x3d80,0xbd353d35,0xbd6dbcc4,0xbcc4bd6d,0x3cc4bd6d,0x3d6dbcc4,
0xbc483d7b,0xbd0e3d55,0xbd553d0e,0xbd7b3c48,0xbd80,0x3cc4bd6d,0x3d35bd35,0x3d6dbcc4,0x3d7b3c48,0x3d553d0e,0x3d0e3d55,0x3c483d7b,0xbd800000,0xbd6dbcc4,0xbd35bd35,0xbcc4bd6d,
0x3c48bd7b,0x3d0ebd55,0x3d55bd0e,0x3d7bbc48,0x3d80,0xbcc43d6d,0xbd353d35,0xbd6d3cc4,0xbd7bbc48,0xbd55bd0e,0xbd0ebd55,0xbc48bd7b,0x3d800000,0x3d6d3cc4,0x3d353d35,0x3cc43d6d,
0x80003d80,0x80003d80,0x80003d80,0x80003d80,0x8000bd80,0x8000bd80,0x8000bd80,0x8000bd80,0x80003d80,0x80003d80,0x80003d80,0x80003d80,0x8000bd80,0x8000bd80,0x8000bd80,0x8000bd80,
0x80003d80,0x80003d80,0x80003d80,0x80003d80,0x8000bd80,0x8000bd80,0x8000bd80,0x8000bd80,0x80003d80,0x80003d80,0x80003d80,0x80003d80,0x8000bd80,0x8000bd80,0x8000bd80,0x8000bd80,
0xbc48bd7b,0xbd0ebd55,0xbd55bd0e,0xbd7bbc48,0x80003d80,0x3cc43d6d,0x3d353d35,0x3d6d3cc4,0xbd7b3c48,0xbd553d0e,0xbd0e3d55,0xbc483d7b,0x3d800000,0x3d6dbcc4,0x3d35bd35,0x3cc4bd6d,
0x3c483d7b,0x3d0e3d55,0x3d553d0e,0x3d7b3c48,0x8000bd80,0xbcc4bd6d,0xbd35bd35,0xbd6dbcc4,0x3d7bbc48,0x3d55bd0e,0x3d0ebd55,0x3c48bd7b,0xbd800000,0xbd6d3cc4,0xbd353d35,0xbcc43d6d,
0x8000bd80,0xbd35bd35,0xbd800000,0xbd353d35,0x3cc43d6d,0x3d6d3cc4,0x3d6dbcc4,0x3cc4bd6d,0x80003d80,0x3d353d35,0x3d800000,0x3d35bd35,0xbcc4bd6d,0xbd6dbcc4,0xbd6d3cc4,0xbcc43d6d,
0x8000bd80,0xbd35bd35,0xbd800000,0xbd353d35,0x3cc43d6d,0x3d6d3cc4,0x3d6dbcc4,0x3cc4bd6d,0x80003d80,0x3d353d35,0x3d800000,0x3d35bd35,0xbcc4bd6d,0xbd6dbcc4,0xbd6d3cc4,0xbcc43d6d,
0x3d55bd0e,0xbc48bd7b,0xbd7bbc48,0xbd0e3d55,0xbd800000,0xbcc43d6d,0x3d353d35,0x3d6dbcc4,0xbd0ebd55,0xbd7b3c48,0xbc483d7b,0x3d553d0e,0x80003d80,0x3d6d3cc4,0x3d35bd35,0xbcc4bd6d,
0xbd553d0e,0x3c483d7b,0x3d7b3c48,0x3d0ebd55,0x3d800000,0x3cc4bd6d,0xbd35bd35,0xbd6d3cc4,0x3d0e3d55,0x3d7bbc48,0x3c48bd7b,0xbd55bd0e,0x8000bd80,0xbd6dbcc4,0xbd353d35,0x3cc43d6d,
0x80003d80,0x3d800000,0x8000bd80,0xbd800000,0xbd35bd35,0xbd353d35,0x3d353d35,0x3d35bd35,0x80003d80,0x3d800000,0x8000bd80,0xbd800000,0xbd35bd35,0xbd353d35,0x3d353d35,0x3d35bd35,
0x80003d80,0x3d800000,0x8000bd80,0xbd800000,0xbd35bd35,0xbd353d35,0x3d353d35,0x3d35bd35,0x80003d80,0x3d800000,0x8000bd80,0xbd800000,0xbd35bd35,0xbd353d35,0x3d353d35,0x3d35bd35,
0x3d553d0e,0x3c48bd7b,0xbd7b3c48,0x3d0e3d55,0x8000bd80,0xbd6d3cc4,0x3d353d35,0x3cc4bd6d,0x3d0ebd55,0xbd7bbc48,0x3c483d7b,0x3d55bd0e,0xbd800000,0x3cc43d6d,0x3d35bd35,0xbd6dbcc4,
0xbd55bd0e,0xbc483d7b,0x3d7bbc48,0xbd0ebd55,0x80003d80,0x3d6dbcc4,0xbd35bd35,0xbcc43d6d,0xbd0e3d55,0x3d7b3c48,0xbc48bd7b,0xbd553d0e,0x3d800000,0xbcc4bd6d,0xbd353d35,0x3d6d3cc4,
0x8000bd80,0xbd353d35,0x3d800000,0xbd35bd35,0x3d6d3cc4,0xbcc4bd6d,0xbcc43d6d,0x3d6dbcc4,0x80003d80,0x3d35bd35,0xbd800000,0x3d353d35,0xbd6dbcc4,0x3cc43d6d,0x3cc4bd6d,0xbd6d3cc4,
0x8000bd80,0xbd353d35,0x3d800000,0xbd35bd35,0x3d6d3cc4,0xbcc4bd6d,0xbcc43d6d,0x3d6dbcc4,0x80003d80,0x3d35bd35,0xbd800000,0x3d353d35,0xbd6dbcc4,0x3cc43d6d,0x3cc4bd6d,0xbd6d3cc4,
0xbc483d7b,0x3d0ebd55,0xbd553d0e,0x3d7bbc48,0x3d800000,0xbd6dbcc4,0x3d353d35,0xbcc4bd6d,0x3d7b3c48,0xbd55bd0e,0x3d0e3d55,0xbc48bd7b,0x8000bd80,0xbcc43d6d,0x3d35bd35,0xbd6d3cc4,
0x3c48bd7b,0xbd0e3d55,0x3d55bd0e,0xbd7b3c48,0xbd800000,0x3d6d3cc4,0xbd35bd35,0x3cc43d6d,0xbd7bbc48,0x3d553d0e,0xbd0ebd55,0x3c483d7b,0x80003d80,0x3cc4bd6d,0xbd353d35,0x3d6dbcc4,
0x3d800000,0x3d800000,0x3d800000,0x3d800000,0xbd800000,0xbd800000,0xbd800000,0xbd800000,0x3d800000,0x3d800000,0x3d800000,0x3d800000,0xbd800000,0xbd800000,0xbd800000,0xbd800000,
0x3d800000,0x3d800000,0x3d800000,0x3d800000,0xbd800000,0xbd800000,0xbd800000,0xbd800000,0x3d800000,0x3d800000,0x3d800000,0x3d800000,0xbd800000,0xbd800000,0xbd800000,0xbd800000,
0xbd7b3c48,0xbd553d0e,0xbd0e3d55,0xbc483d7b,0x3d800000,0x3d6dbcc4,0x3d35bd35,0x3cc4bd6d,0x3c483d7b,0x3d0e3d55,0x3d553d0e,0x3d7b3c48,0xbd80,0xbcc4bd6d,0xbd35bd35,0xbd6dbcc4,
0x3d7bbc48,0x3d55bd0e,0x3d0ebd55,0x3c48bd7b,0xbd800000,0xbd6d3cc4,0xbd353d35,0xbcc43d6d,0xbc48bd7b,0xbd0ebd55,0xbd55bd0e,0xbd7bbc48,0x3d80,0x3cc43d6d,0x3d353d35,0x3d6d3cc4,
0xbd800000,0xbd353d35,0x3d80,0x3d353d35,0x3d6dbcc4,0x3cc4bd6d,0xbcc4bd6d,0xbd6dbcc4,0x3d800000,0x3d35bd35,0xbd80,0xbd35bd35,0xbd6d3cc4,0xbcc43d6d,0x3cc43d6d,0x3d6d3cc4,
0xbd800000,0xbd353d35,0x3d80,0x3d353d35,0x3d6dbcc4,0x3cc4bd6d,0xbcc4bd6d,0xbd6dbcc4,0x3d800000,0x3d35bd35,0xbd80,0xbd35bd35,0xbd6d3cc4,0xbcc43d6d,0x3cc43d6d,0x3d6d3cc4,
0xbd0ebd55,0xbd7b3c48,0xbc483d7b,0x3d553d0e,0x3d80,0x3d6d3cc4,0x3d35bd35,0xbcc4bd6d,0xbd553d0e,0x3c483d7b,0x3d7b3c48,0x3d0ebd55,0x3d800000,0x3cc4bd6d,0xbd35bd35,0xbd6d3cc4,
0x3d0e3d55,0x3d7bbc48,0x3c48bd7b,0xbd55bd0e,0xbd80,0xbd6dbcc4,0xbd353d35,0x3cc43d6d,0x3d55bd0e,0xbc48bd7b,0xbd7bbc48,0xbd0e3d55,0xbd800000,0xbcc43d6d,0x3d353d35,0x3d6dbcc4,
0x3d800000,0xbd80,0xbd800000,0x3d80,0xbd353d35,0x3d353d35,0x3d35bd35,0xbd35bd35,0x3d800000,0xbd80,0xbd800000,0x3d80,0xbd353d35,0x3d353d35,0x3d35bd35,0xbd35bd35,
0x3d800000,0xbd80,0xbd800000,0x3d80,0xbd353d35,0x3d353d35,0x3d35bd35,0xbd35bd35,0x3d800000,0xbd80,0xbd800000,0x3d80,0xbd353d35,0x3d353d35,0x3d35bd35,0xbd35bd35,
0x3d0ebd55,0xbd7bbc48,0x3c483d7b,0x3d55bd0e,0xbd800000,0x3cc43d6d,0x3d35bd35,0xbd6dbcc4,0xbd55bd0e,0xbc483d7b,0x3d7bbc48,0xbd0ebd55,0x3d80,0x3d6dbcc4,0xbd35bd35,0xbcc43d6d,
0xbd0e3d55,0x3d7b3c48,0xbc48bd7b,0xbd553d0e,0x3d800000,0xbcc4bd6d,0xbd353d35,0x3d6d3cc4,0x3d553d0e,0x3c48bd7b,0xbd7b3c48,0x3d0e3d55,0xbd80,0xbd6d3cc4,0x3d353d35,0x3cc4bd6d,
0xbd800000,0x3d353d35,0xbd80,0xbd353d35,0x3cc4bd6d,0xbd6d3cc4,0x3d6d3cc4,0xbcc4bd6d,0x3d800000,0xbd35bd35,0x3d80,0x3d35bd35,0xbcc43d6d,0x3d6dbcc4,0xbd6dbcc4,0x3cc43d6d,
0xbd800000,0x3d353d35,0xbd80,0xbd353d35,0x3cc4bd6d,0xbd6d3cc4,0x3d6d3cc4,0xbcc4bd6d,0x3d800000,0xbd35bd35,0x3d80,0x3d35bd35,0xbcc43d6d,0x3d6dbcc4,0xbd6dbcc4,0x3cc43d6d,
0x3d7b3c48,0xbd55bd0e,0x3d0e3d55,0xbc48bd7b,0xbd80,0xbcc43d6d,0x3d35bd35,0xbd6d3cc4,0x3c48bd7b,0xbd0e3d55,0x3d55bd0e,0xbd7b3c48,0xbd800000,0x3d6d3cc4,0xbd35bd35,0x3cc43d6d,
0xbd7bbc48,0x3d553d0e,0xbd0ebd55,0x3c483d7b,0x3d80,0x3cc4bd6d,0xbd353d35,0x3d6dbcc4,0xbc483d7b,0x3d0ebd55,0xbd553d0e,0x3d7bbc48,0x3d800000,0xbd6dbcc4,0x3d353d35,0xbcc4bd6d,
0x80003d80,0x8000bd80,0x80003d80,0x8000bd80,0xbd800000,0x3d800000,0xbd800000,0x3d800000,0x80003d80,0x8000bd80,0x80003d80,0x8000bd80,0xbd800000,0x3d800000,0xbd800000,0x3d800000,
0x80003d80,0x8000bd80,0x80003d80,0x8000bd80,0xbd800000,0x3d800000,0xbd800000,0x3d800000,0x80003d80,0x8000bd80,0x80003d80,0x8000bd80,0xbd800000,0x3d800000,0xbd800000,0x3d800000,
0xbd7b3c48,0x3d55bd0e,0xbd0e3d55,0x3c48bd7b,0x80003d80,0xbcc4bd6d,0x3d353d35,0xbd6dbcc4,0x3c483d7b,0xbd0ebd55,0x3d553d0e,0xbd7bbc48,0x3d800000,0xbd6d3cc4,0x3d35bd35,0xbcc43d6d,
0x3d7bbc48,0xbd553d0e,0x3d0ebd55,0xbc483d7b,0x8000bd80,0x3cc43d6d,0xbd35bd35,0x3d6d3cc4,0xbc48bd7b,0x3d0e3d55,0xbd55bd0e,0x3d7b3c48,0xbd800000,0x3d6dbcc4,0xbd353d35,0x3cc4bd6d,
0x8000bd80,0x3d353d35,0xbd800000,0x3d35bd35,0x3d6dbcc4,0xbcc43d6d,0xbcc4bd6d,0x3d6d3cc4,0x80003d80,0xbd35bd35,0x3d800000,0xbd353d35,0xbd6d3cc4,0x3cc4bd6d,0x3cc43d6d,0xbd6dbcc4,
0x8000bd80,0x3d353d35,0xbd800000,0x3d35bd35,0x3d6dbcc4,0xbcc43d6d,0xbcc4bd6d,0x3d6d3cc4,0x80003d80,0xbd35bd35,0x3d800000,0xbd353d35,0xbd6d3cc4,0x3cc4bd6d,0x3cc43d6d,0xbd6dbcc4,
0xbd0ebd55,0x3d7bbc48,0xbc483d7b,0xbd55bd0e,0xbd800000,0x3cc4bd6d,0x3d353d35,0xbd6d3cc4,0xbd553d0e,0xbc48bd7b,0x3d7b3c48,0xbd0e3d55,0x80003d80,0xbd6dbcc4,0x3d35bd35,0x3cc43d6d,
0x3d0e3d55,0xbd7b3c48,0x3c48bd7b,0x3d553d0e,0x3d800000,0xbcc43d6d,0xbd35bd35,0x3d6dbcc4,0x3d55bd0e,0x3c483d7b,0xbd7bbc48,0x3d0ebd55,0x8000bd80,0x3d6d3cc4,0xbd353d35,0xbcc4bd6d,
0x80003d80,0xbd800000,0x8000bd80,0x3d800000,0xbd353d35,0xbd35bd35,0x3d35bd35,0x3d353d35,0x80003d80,0xbd800000,0x8000bd80,0x3d800000,0xbd353d35,0xbd35bd35,0x3d35bd35,0x3d353d35,
0x80003d80,0xbd800000,0x8000bd80,0x3d800000,0xbd353d35,0xbd35bd35,0x3d35bd35,0x3d353d35,0x80003d80,0xbd800000,0x8000bd80,0x3d800000,0xbd353d35,0xbd35bd35,0x3d35bd35,0x3d353d35,
0x3d0ebd55,0x3d7b3c48,0x3c483d7b,0xbd553d0e,0x8000bd80,0x3d6dbcc4,0x3d353d35,0xbcc43d6d,0xbd55bd0e,0x3c48bd7b,0x3d7bbc48,0x3d0e3d55,0xbd800000,0xbcc4bd6d,0x3d35bd35,0x3d6d3cc4,
0xbd0e3d55,0xbd7bbc48,0xbc48bd7b,0x3d55bd0e,0x80003d80,0xbd6d3cc4,0xbd35bd35,0x3cc4bd6d,0x3d553d0e,0xbc483d7b,0xbd7b3c48,0xbd0ebd55,0x3d800000,0x3cc43d6d,0xbd353d35,0xbd6dbcc4,
0x8000bd80,0x3d35bd35,0x3d800000,0x3d353d35,0x3cc4bd6d,0x3d6dbcc4,0x3d6d3cc4,0x3cc43d6d,0x80003d80,0xbd353d35,0xbd800000,0xbd35bd35,0xbcc43d6d,0xbd6d3cc4,0xbd6dbcc4,0xbcc4bd6d,
0x8000bd80,0x3d35bd35,0x3d800000,0x3d353d35,0x3cc4bd6d,0x3d6dbcc4,0x3d6d3cc4,0x3cc43d6d,0x80003d80,0xbd353d35,0xbd800000,0xbd35bd35,0xbcc43d6d,0xbd6d3cc4,0xbd6dbcc4,0xbcc4bd6d,
0x3d7b3c48,0x3d553d0e,0x3d0e3d55,0x3c483d7b,0x3d800000,0x3d6d3cc4,0x3d353d35,0x3cc43d6d,0x3c48bd7b,0x3d0ebd55,0x3d55bd0e,0x3d7bbc48,0x8000bd80,0x3cc4bd6d,0x3d35bd35,0x3d6dbcc4,
0xbd7bbc48,0xbd55bd0e,0xbd0ebd55,0xbc48bd7b,0xbd800000,0xbd6dbcc4,0xbd35bd35,0xbcc4bd6d,0xbc483d7b,0xbd0e3d55,0xbd553d0e,0xbd7b3c48,0x80003d80,0xbcc43d6d,0xbd353d35,0xbd6d3cc4,
0x3d800000,0xbd800000,0x3d800000,0xbd800000,0x3d80,0xbd80,0x3d80,0xbd80,0x3d800000,0xbd800000,0x3d800000,0xbd800000,0x3d80,0xbd80,0x3d80,0xbd80,
0x3d800000,0xbd800000,0x3d800000,0xbd800000,0x3d80,0xbd80,0x3d80,0xbd80,0x3d800000,0xbd800000,0x3d800000,0xbd800000,0x3d80,0xbd80,0x3d80,0xbd80,
0x3c483d7b,0xbd0ebd55,0x3d553d0e,0xbd7bbc48,0x3d800000,0xbd6d3cc4,0x3d35bd35,0xbcc43d6d,0x3d7bbc48,0xbd553d0e,0x3d0ebd55,0xbc483d7b,0xbd80,0x3cc43d6d,0xbd35bd35,0x3d6d3cc4,
0xbc48bd7b,0x3d0e3d55,0xbd55bd0e,0x3d7b3c48,0xbd800000,0x3d6dbcc4,0xbd353d35,0x3cc4bd6d,0xbd7b3c48,0x3d55bd0e,0xbd0e3d55,0x3c48bd7b,0x3d80,0xbcc4bd6d,0x3d353d35,0xbd6dbcc4,
0xbd800000,0x3d35bd35,0x3d80,0xbd35bd35,0xbcc4bd6d,0x3d6d3cc4,0xbd6d3cc4,0x3cc4bd6d,0x3d800000,0xbd353d35,0xbd80,0x3d353d35,0x3cc43d6d,0xbd6dbcc4,0x3d6dbcc4,0xbcc43d6d,
0xbd800000,0x3d35bd35,0x3d80,0xbd35bd35,0xbcc4bd6d,0x3d6d3cc4,0xbd6d3cc4,0x3cc4bd6d,0x3d800000,0xbd353d35,0xbd80,0x3d353d35,0x3cc43d6d,0xbd6dbcc4,0x3d6dbcc4,0xbcc43d6d,
0xbd553d0e,0xbc48bd7b,0x3d7b3c48,0xbd0e3d55,0x3d80,0xbd6dbcc4,0x3d35bd35,0x3cc43d6d,0x3d0e3d55,0xbd7b3c48,0x3c48bd7b,0x3d553d0e,0x3d800000,0xbcc43d6d,0xbd35bd35,0x3d6dbcc4,
0x3d55bd0e,0x3c483d7b,0xbd7bbc48,0x3d0ebd55,0xbd80,0x3d6d3cc4,0xbd353d35,0xbcc4bd6d,0xbd0ebd55,0x3d7bbc48,0xbc483d7b,0xbd55bd0e,0xbd800000,0x3cc4bd6d,0x3d353d35,0xbd6d3cc4,
0x3d800000,0x3d80,0xbd800000,0xbd80,0x3d353d35,0xbd353d35,0xbd35bd35,0x3d35bd35,0x3d800000,0x3d80,0xbd800000,0xbd80,0x3d353d35,0xbd353d35,0xbd35bd35,0x3d35bd35,
0x3d800000,0x3d80,0xbd800000,0xbd80,0x3d353d35,0xbd353d35,0xbd35bd35,0x3d35bd35,0x3d800000,0x3d80,0xbd800000,0xbd80,0x3d353d35,0xbd353d35,0xbd35bd35,0x3d35bd35,
0xbd55bd0e,0x3c48bd7b,0x3d7bbc48,0x3d0e3d55,0xbd800000,0xbcc4bd6d,0x3d35bd35,0x3d6d3cc4,0xbd0e3d55,0xbd7bbc48,0xbc48bd7b,0x3d55bd0e,0x3d80,0xbd6d3cc4,0xbd35bd35,0x3cc4bd6d,
0x3d553d0e,0xbc483d7b,0xbd7b3c48,0xbd0ebd55,0x3d800000,0x3cc43d6d,0xbd353d35,0xbd6dbcc4,0x3d0ebd55,0x3d7b3c48,0x3c483d7b,0xbd553d0e,0xbd80,0x3d6dbcc4,0x3d353d35,0xbcc43d6d,
0xbd800000,0xbd35bd35,0xbd80,0x3d35bd35,0xbd6dbcc4,0xbcc4bd6d,0x3cc4bd6d,0x3d6dbcc4,0x3d800000,0x3d353d35,0x3d80,0xbd353d35,0x3d6d3cc4,0x3cc43d6d,0xbcc43d6d,0xbd6d3cc4,
0xbd800000,0xbd35bd35,0xbd80,0x3d35bd35,0xbd6dbcc4,0xbcc4bd6d,0x3cc4bd6d,0x3d6dbcc4,0x3d800000,0x3d353d35,0x3d80,0xbd353d35,0x3d6d3cc4,0x3cc43d6d,0xbcc43d6d,0xbd6d3cc4,
0x3c48bd7b,0x3d0ebd55,0x3d55bd0e,0x3d7bbc48,0xbd80,0x3cc4bd6d,0x3d35bd35,0x3d6dbcc4,0xbd7bbc48,0xbd55bd0e,0xbd0ebd55,0xbc48bd7b,0xbd800000,0xbd6dbcc4,0xbd35bd35,0xbcc4bd6d,
0xbc483d7b,0xbd0e3d55,0xbd553d0e,0xbd7b3c48,0x3d80,0xbcc43d6d,0xbd353d35,0xbd6d3cc4,0x3d7b3c48,0x3d553d0e,0x3d0e3d55,0x3c483d7b,0x3d800000,0x3d6d3cc4,0x3d353d35,0x3cc43d6d,
0x3f003f00,0xbf003f00,0x3f003f00,0xbf003f00,0x3f003f00,0xbf003f00,0x3f003f00,0xbf003f00,0x3f003f00,0xbf003f00,0x3f003f00,0xbf003f00,0x3f003f00,0xbf003f00,0x3f003f00,0xbf003f00,
0x3eff3f00,0xbd490000,0x3ea23eb5,0xbec6beb5,0x3ef53efb,0xbe15bdc8,0x3e713e8e,0xbee2bed5,0x3ee23eed,0xbe71be44,0x3e153e44,0xbef5beed,0x3ec63ed5,0xbea2be8e,0x3d493dc8,0xbeffbefb,
0x3efb3f00,0xbdc80000,0xbdc80000,0xbefbbf00,0x3ed53eed,0xbe8ebe44,0xbe8ebe44,0xbed5beed,0x3e8e3eb5,0xbed5beb5,0xbed5beb5,0xbe8ebeb5,0x3dc83e44,0xbefbbeed,0xbefbbeed,0xbdc8be44,
0x3ef53f00,0xbe150000,0xbee2beb5,0xbe71beb5,0x3ea23ed5,0xbec6be8e,0xbeffbefb,0x3d49bdc8,0x3d493e44,0xbeffbeed,0xbec6beed,0x3ea23e44,0xbe71bdc8,0xbee2befb,0xbe15be8e,0x3ef53ed5,
0x3eed3f00,0xbe440000,0xbeedbf00,0x3e440000,0x3e443eb5,0xbeedbeb5,0xbe44beb5,0x3eed3eb5,0xbe440000,0xbeedbf00,0x3e440000,0x3eed3f00,0xbeedbeb5,0xbe44beb5,0x3eed3eb5,0x3e443eb5,
0x3ee23f00,0xbe710000,0xbe15beb5,0x3ef53eb5,0x3d493e8e,0xbeffbed5,0x3ea23dc8,0x3ec63efb,0xbec6be44,0xbea2beed,0x3eff3eed,0xbd493e44,0xbef5befb,0x3e15bdc8,0x3e713ed5,0xbee2be8e,
0x3ed53f00,0xbe8e0000,0x3e8e0000,0x3ed53f00,0xbdc83e44,0xbefbbeed,0x3efb3eed,0xbdc83e44,0xbefbbeb5,0xbdc8beb5,0x3dc83eb5,0xbefbbeb5,0xbe8ebeed,0x3ed53e44,0xbed5be44,0xbe8ebeed,
0x3ec63f00,0xbea20000,0x3eff3eb5,0x3d493eb5,0xbe713dc8,0xbee2befb,0x3e153ed5,0xbef5be8e,0xbef5beed,0x3e15be44,0xbee2be44,0xbe71beed,0x3d49be8e,0x3eff3ed5,0xbea2befb,0x3ec63dc8,
0x3eb53f00,0xbeb50000,0x3eb53f00,0xbeb50000,0xbeb50000,0xbeb5bf00,0xbeb50000,0xbeb5bf00,0xbeb5bf00,0x3eb50000,0xbeb5bf00,0x3eb50000,0x3eb50000,0x3eb53f00,0x3eb50000,0x3eb53f00,
0x3ea23f00,0xbec60000,0xbd493eb5,0xbeffbeb5,0xbee2bdc8,0xbe71befb,0xbef5bed5,0x3e15be8e,0xbe15beed,0x3ef53e44,0x3e71be44,0x3ee23eed,0x3eff3e8e,0x3d493ed5,0x3ec63efb,0xbea23dc8,
0x3e8e3f00,0xbed50000,0xbed50000,0xbe8ebf00,0xbefbbe44,0xbdc8beed,0xbdc8beed,0x3efb3e44,0x3dc8beb5,0x3efb3eb5,0x3efb3eb5,0xbdc83eb5,0x3ed53eed,0xbe8e3e44,0xbe8e3e44,0xbed5beed,
0x3e713f00,0xbee20000,0xbef5beb5,0x3e15beb5,0xbeffbe8e,0x3d49bed5,0x3ec6bdc8,0x3ea23efb,0x3ea2be44,0x3ec63eed,0x3d493eed,0xbeffbe44,0x3e153efb,0xbef5bdc8,0xbee2bed5,0x3e71be8e,
0x3e443f00,0xbeed0000,0xbe44bf00,0x3eed0000,0xbeedbeb5,0x3e44beb5,0x3eed3eb5,0xbe443eb5,0x3eed0000,0x3e443f00,0xbeed0000,0xbe44bf00,0xbe443eb5,0xbeedbeb5,0x3e44beb5,0x3eed3eb5,
0x3e153f00,0xbef50000,0x3e71beb5,0x3ee23eb5,0xbec6bed5,0x3ea2be8e,0x3d493efb,0xbeffbdc8,0x3eff3e44,0xbd493eed,0xbea2beed,0x3ec6be44,0xbee23dc8,0xbe71befb,0x3ef53e8e,0xbe153ed5,
0x3dc83f00,0xbefb0000,0x3efb0000,0x3dc83f00,0xbe8ebeed,0x3ed5be44,0xbed53e44,0xbe8ebeed,0x3ed53eb5,0xbe8e3eb5,0x3e8ebeb5,0x3ed53eb5,0xbefbbe44,0x3dc8beed,0xbdc83eed,0xbefbbe44,
0x3d493f00,0xbeff0000,0x3ec63eb5,0xbea23eb5,0xbe15befb,0x3ef5bdc8,0xbee2be8e,0x3e71bed5,0x3e713eed,0xbee23e44,0x3ef53e44,0xbe153eed,0xbea2bed5,0x3ec6be8e,0xbeffbdc8,0x3d49befb,
0x3f00,0xbf000000,0x3f00,0xbf000000,0xbf00,0x3f000000,0xbf00,0x3f000000,0x3f00,0xbf000000,0x3f00,0xbf000000,0xbf00,0x3f000000,0xbf00,0x3f000000,
0xbd493f00,0xbeff0000,0xbec63eb5,0xbea2beb5,0x3e15befb,0x3ef53dc8,0x3ee2be8e,0x3e713ed5,0xbe713eed,0xbee2be44,0xbef53e44,0xbe15beed,0x3ea2bed5,0x3ec63e8e,0x3effbdc8,0x3d493efb,
0xbdc83f00,0xbefb0000,0xbefb0000,0x3dc8bf00,0x3e8ebeed,0x3ed53e44,0x3ed53e44,0xbe8e3eed,0xbed53eb5,0xbe8ebeb5,0xbe8ebeb5,0x3ed5beb5,0x3efbbe44,0x3dc83eed,0x3dc83eed,0xbefb3e44,
0xbe153f00,0xbef50000,0xbe71beb5,0x3ee2beb5,0x3ec6bed5,0x3ea23e8e,0xbd493efb,0xbeff3dc8,0xbeff3e44,0xbd49beed,0x3ea2beed,0x3ec63e44,0x3ee23dc8,0xbe713efb,0xbef53e8e,0xbe15bed5,
0xbe443f00,0xbeed0000,0x3e44bf00,0x3eed0000,0x3eedbeb5,0x3e443eb5,0xbeed3eb5,0xbe44beb5,0xbeed0000,0x3e44bf00,0x3eed0000,0xbe443f00,0x3e443eb5,0xbeed3eb5,0xbe44beb5,0x3eedbeb5,
0xbe713f00,0xbee20000,0x3ef5beb5,0x3e153eb5,0x3effbe8e,0x3d493ed5,0xbec6bdc8,0x3ea2befb,0xbea2be44,0x3ec6beed,0xbd493eed,0xbeff3e44,0xbe153efb,0xbef53dc8,0x3ee2bed5,0x3e713e8e,
0xbe8e3f00,0xbed50000,0x3ed50000,0xbe8e3f00,0x3efbbe44,0xbdc83eed,0x3dc8beed,0x3efbbe44,0xbdc8beb5,0x3efbbeb5,0xbefb3eb5,0xbdc8beb5,0xbed53eed,0xbe8ebe44,0x3e8e3e44,0xbed53eed,
0xbea23f00,0xbec60000,0x3d493eb5,0xbeff3eb5,0x3ee2bdc8,0xbe713efb,0x3ef5bed5,0x3e153e8e,0x3e15beed,0x3ef5be44,0xbe71be44,0x3ee2beed,0xbeff3e8e,0x3d49bed5,0xbec63efb,0xbea2bdc8,
0xbeb53f00,0xbeb50000,0xbeb53f00,0xbeb50000,0x3eb50000,0xbeb53f00,0x3eb50000,0xbeb53f00,0x3eb5bf00,0x3eb50000,0x3eb5bf00,0x3eb50000,0xbeb50000,0x3eb5bf00,0xbeb50000,0x3eb5bf00,
0xbec63f00,0xbea20000,0xbeff3eb5,0x3d49beb5,0x3e713dc8,0xbee23efb,0xbe153ed5,0xbef53e8e,0x3ef5beed,0x3e153e44,0x3ee2be44,0xbe713eed,0xbd49be8e,0x3effbed5,0x3ea2befb,0x3ec6bdc8,
0xbed53f00,0xbe8e0000,0xbe8e0000,0x3ed5bf00,0x3dc83e44,0xbefb3eed,0xbefb3eed,0xbdc8be44,0x3efbbeb5,0xbdc83eb5,0xbdc83eb5,0xbefb3eb5,0x3e8ebeed,0x3ed5be44,0x3ed5be44,0xbe8e3eed,
0xbee23f00,0xbe710000,0x3e15beb5,0x3ef5beb5,0xbd493e8e,0xbeff3ed5,0xbea23dc8,0x3ec6befb,0x3ec6be44,0xbea23eed,0xbeff3eed,0xbd49be44,0x3ef5befb,0x3e153dc8,0xbe713ed5,0xbee23e8e,
0xbeed3f00,0xbe440000,0x3eedbf00,0x3e440000,0xbe443eb5,0xbeed3eb5,0x3e44beb5,0x3eedbeb5,0x3e440000,0xbeed3f00,0xbe440000,0x3eedbf00,0x3eedbeb5,0xbe443eb5,0xbeed3eb5,0x3e44beb5,
0xbef53f00,0xbe150000,0x3ee2beb5,0xbe713eb5,0xbea23ed5,0xbec63e8e,0x3effbefb,0x3d493dc8,0xbd493e44,0xbeff3eed,0x3ec6beed,0x3ea2be44,0x3e71bdc8,0xbee23efb,0x3e15be8e,0x3ef5bed5,
0xbefb3f00,0xbdc80000,0x3dc80000,0xbefb3f00,0xbed53eed,0xbe8e3e44,0x3e8ebe44,0xbed53eed,0xbe8e3eb5,0xbed53eb5,0x3ed5beb5,0xbe8e3eb5,0xbdc83e44,0xbefb3eed,0x3efbbeed,0xbdc83e44,
0xbeff3f00,0xbd490000,0xbea23eb5,0xbec63eb5,0xbef53efb,0xbe153dc8,0xbe713e8e,0xbee23ed5,0xbee23eed,0xbe713e44,0xbe153e44,0xbef53eed,0xbec63ed5,0xbea23e8e,0xbd493dc8,0xbeff3efb,
0x3f003f00,0xbf003f00,0x3f003f00,0xbf003f00,0x3f003f00,0xbf003f00,0x3f003f00,0xbf003f00,0x3f003f00,0xbf003f00,0x3f003f00,0xbf003f00,0x3f003f00,0xbf003f00,0x3f003f00,0xbf003f00,
0xbd490000,0xbeffbf00,0xbec6beb5,0xbea2beb5,0xbe15bdc8,0xbef5befb,0xbee2bed5,0xbe71be8e,0xbe71be44,0xbee2beed,0xbef5beed,0xbe15be44,0xbea2be8e,0xbec6bed5,0xbeffbefb,0xbd49bdc8,
0xbefbbf00,0x3dc80000,0x3dc80000,0x3efb3f00,0xbed5beed,0x3e8e3e44,0x3e8e3e44,0x3ed53eed,0xbe8ebeb5,0x3ed53eb5,0x3ed53eb5,0x3e8e3eb5,0xbdc8be44,0x3efb3eed,0x3efb3eed,0x3dc83e44,
0x3e150000,0x3ef53f00,0x3e713eb5,0xbee2beb5,0x3ec63e8e,0x3ea23ed5,0xbd493dc8,0xbeffbefb,0x3eff3eed,0x3d493e44,0xbea2be44,0xbec6beed,0x3ee23efb,0xbe71bdc8,0xbef5bed5,0xbe15be8e,
0x3eed3f00,0xbe440000,0xbeedbf00,0x3e440000,0x3e443eb5,0xbeedbeb5,0xbe44beb5,0x3eed3eb5,0xbe440000,0xbeedbf00,0x3e440000,0x3eed3f00,0xbeedbeb5,0xbe44beb5,0x3eed3eb5,0x3e443eb5,
0xbe710000,0xbee2bf00,0x3ef53eb5,0x3e153eb5,0xbeffbed5,0xbd49be8e,0x3ec63efb,0xbea2bdc8,0xbea2beed,0x3ec63e44,0xbd493e44,0xbeffbeed,0x3e15bdc8,0x3ef53efb,0xbee2be8e,0xbe71bed5,
0xbed5bf00,0x3e8e0000,0xbe8e0000,0xbed5bf00,0x3dc8be44,0x3efb3eed,0xbefbbeed,0x3dc8be44,0x3efb3eb5,0x3dc83eb5,0xbdc8beb5,0x3efb3eb5,0x3e8e3eed,0xbed5be44,0x3ed53e44,0x3e8e3eed,
0x3ea20000,0x3ec63f00,0xbd49beb5,0x3eff3eb5,0x3ee23efb,0xbe713dc8,0x3ef53e8e,0x3e153ed5,0xbe153e44,0xbef5beed,0x3e713eed,0xbee2be44,0xbeffbed5,0x3d49be8e,0xbec6bdc8,0xbea2befb,
0x3eb53f00,0xbeb50000,0x3eb53f00,0xbeb50000,0xbeb50000,0xbeb5bf00,0xbeb50000,0xbeb5bf00,0xbeb5bf00,0x3eb50000,0xbeb5bf00,0x3eb50000,0x3eb50000,0x3eb53f00,0x3eb50000,0x3eb53f00,
0xbec60000,0xbea2bf00,0xbeffbeb5,0x3d49beb5,0xbe71befb,0x3ee23dc8,0x3e15be8e,0x3ef53ed5,0x3ef53e44,0x3e153eed,0x3ee23eed,0xbe713e44,0x3d493ed5,0xbeffbe8e,0xbea23dc8,0xbec6befb,
0xbe8ebf00,0x3ed50000,0x3ed50000,0x3e8e3f00,0x3efb3e44,0x3dc83eed,0x3dc83eed,0xbefbbe44,0xbdc83eb5,0xbefbbeb5,0xbefbbeb5,0x3dc8beb5,0xbed5beed,0x3e8ebe44,0x3e8ebe44,0x3ed53eed,
0x3ee20000,0x3e713f00,0xbe153eb5,0xbef5beb5,0xbd493ed5,0xbeffbe8e,0xbea2befb,0x3ec6bdc8,0xbec6beed,0x3ea2be44,0x3eff3e44,0x3d493eed,0x3ef53dc8,0x3e153efb,0xbe713e8e,0xbee2bed5,
0x3e443f00,0xbeed0000,0xbe44bf00,0x3eed0000,0xbeedbeb5,0x3e44beb5,0x3eed3eb5,0xbe443eb5,0x3eed0000,0x3e443f00,0xbeed0000,0xbe44bf00,0xbe443eb5,0xbeedbeb5,0x3e44beb5,0x3eed3eb5,
0xbef50000,0xbe15bf00,0x3ee23eb5,0xbe713eb5,0x3ea2be8e,0x3ec63ed5,0xbeffbdc8,0xbd49befb,0xbd493eed,0xbeffbe44,0x3ec6be44,0x3ea23eed,0xbe71befb,0x3ee2bdc8,0xbe153ed5,0xbef5be8e,
0xbdc8bf00,0x3efb0000,0xbefb0000,0xbdc8bf00,0x3e8e3eed,0xbed53e44,0x3ed5be44,0x3e8e3eed,0xbed5beb5,0x3e8ebeb5,0xbe8e3eb5,0xbed5beb5,0x3efb3e44,0xbdc83eed,0x3dc8beed,0x3efb3e44,
0x3eff0000,0x3d493f00,0x3ea2beb5,0x3ec63eb5,0xbef53dc8,0xbe15befb,0xbe713ed5,0xbee2be8e,0x3ee2be44,0x3e713eed,0x3e15beed,0x3ef53e44,0xbec63e8e,0xbea2bed5,0xbd493efb,0xbeffbdc8,
0x3f00,0xbf000000,0x3f00,0xbf000000,0xbf00,0x3f000000,0xbf00,0x3f000000,0x3f00,0xbf000000,0x3f00,0xbf000000,0xbf00,0x3f000000,0xbf00,0x3f000000,
0xbeff0000,0x3d49bf00,0xbea2beb5,0x3ec6beb5,0x3ef53dc8,0xbe153efb,0x3e713ed5,0xbee23e8e,0xbee2be44,0x3e71beed,0xbe15beed,0x3ef5be44,0x3ec63e8e,0xbea23ed5,0x3d493efb,0xbeff3dc8,
0x3dc8bf00,0x3efb0000,0x3efb0000,0xbdc83f00,0xbe8e3eed,0xbed5be44,0xbed5be44,0x3e8ebeed,0x3ed5beb5,0x3e8e3eb5,0x3e8e3eb5,0xbed53eb5,0xbefb3e44,0xbdc8beed,0xbdc8beed,0x3efbbe44,
0x3ef50000,0xbe153f00,0xbee23eb5,0xbe71beb5,0xbea2be8e,0x3ec6bed5,0x3effbdc8,0xbd493efb,0x3d493eed,0xbeff3e44,0xbec6be44,0x3ea2beed,0x3e71befb,0x3ee23dc8,0x3e153ed5,0xbef53e8e,
0xbe443f00,0xbeed0000,0x3e44bf00,0x3eed0000,0x3eedbeb5,0x3e443eb5,0xbeed3eb5,0xbe44beb5,0xbeed0000,0x3e44bf00,0x3eed0000,0xbe443f00,0x3e443eb5,0xbeed3eb5,0xbe44beb5,0x3eedbeb5,
0xbee20000,0x3e71bf00,0x3e153eb5,0xbef53eb5,0x3d493ed5,0xbeff3e8e,0x3ea2befb,0x3ec63dc8,0x3ec6beed,0x3ea23e44,0xbeff3e44,0x3d49beed,0xbef53dc8,0x3e15befb,0x3e713e8e,0xbee23ed5,
0x3e8ebf00,0x3ed50000,0xbed50000,0x3e8ebf00,0xbefb3e44,0x3dc8beed,0xbdc83eed,0xbefb3e44,0x3dc83eb5,0xbefb3eb5,0x3efbbeb5,0x3dc83eb5,0x3ed5beed,0x3e8e3e44,0xbe8ebe44,0x3ed5beed,
0x3ec60000,0xbea23f00,0x3effbeb5,0x3d493eb5,0x3e71befb,0x3ee2bdc8,0xbe15be8e,0x3ef5bed5,0xbef53e44,0x3e15beed,0xbee23eed,0xbe71be44,0xbd493ed5,0xbeff3e8e,0x3ea23dc8,0xbec63efb,
0xbeb53f00,0xbeb50000,0xbeb53f00,0xbeb50000,0x3eb50000,0xbeb53f00,0x3eb50000,0xbeb53f00,0x3eb5bf00,0x3eb50000,0x3eb5bf00,0x3eb50000,0xbeb50000,0x3eb5bf00,0xbeb50000,0x3eb5bf00,
0xbea20000,0x3ec6bf00,0x3d49beb5,0x3effbeb5,0xbee23efb,0xbe71bdc8,0xbef53e8e,0x3e15bed5,0x3e153e44,0xbef53eed,0xbe713eed,0xbee23e44,0x3effbed5,0x3d493e8e,0x3ec6bdc8,0xbea23efb,
0x3ed5bf00,0x3e8e0000,0x3e8e0000,0xbed53f00,0xbdc8be44,0x3efbbeed,0x3efbbeed,0x3dc83e44,0xbefb3eb5,0x3dc8beb5,0x3dc8beb5,0x3efbbeb5,0xbe8e3eed,0xbed53e44,0xbed53e44,0x3e8ebeed,
0x3e710000,0xbee23f00,0xbef53eb5,0x3e15beb5,0x3effbed5,0xbd493e8e,0xbec63efb,0xbea23dc8,0x3ea2beed,0x3ec6be44,0x3d493e44,0xbeff3eed,0xbe15bdc8,0x3ef5befb,0x3ee2be8e,0xbe713ed5,
0xbeed3f00,0xbe440000,0x3eedbf00,0x3e440000,0xbe443eb5,0xbeed3eb5,0x3e44beb5,0x3eedbeb5,0x3e440000,0xbeed3f00,0xbe440000,0x3eedbf00,0x3eedbeb5,0xbe443eb5,0xbeed3eb5,0x3e44beb5,
0xbe150000,0x3ef5bf00,0xbe713eb5,0xbee23eb5,0xbec63e8e,0x3ea2bed5,0x3d493dc8,0xbeff3efb,0xbeff3eed,0x3d49be44,0x3ea2be44,0xbec63eed,0xbee23efb,0xbe713dc8,0x3ef5bed5,0xbe153e8e,
0x3efbbf00,0x3dc80000,0xbdc80000,0x3efbbf00,0x3ed5beed,0x3e8ebe44,0xbe8e3e44,0x3ed5beed,0x3e8ebeb5,0x3ed5beb5,0xbed53eb5,0x3e8ebeb5,0x3dc8be44,0x3efbbeed,0xbefb3eed,0x3dc8be44,
0x3d490000,0xbeff3f00,0x3ec6beb5,0xbea23eb5,0x3e15bdc8,0xbef53efb,0x3ee2bed5,0xbe713e8e,0x3e71be44,0xbee23eed,0x3ef5beed,0xbe153e44,0x3ea2be8e,0xbec63ed5,0x3effbefb,0xbd493dc8,
0x3f003f00,0xbf003f00,0x3f003f00,0xbf003f00,0x3f003f00,0xbf003f00,0x3f003f00,0xbf003f00,0x3f003f00,0xbf003f00,0x3f003f00,0xbf003f00,0x3f003f00,0xbf003f00,0x3f003f00,0xbf003f00,
0xbeffbf00,0x3d490000,0xbea2beb5,0x3ec63eb5,0xbef5befb,0x3e153dc8,0xbe71be8e,0x3ee23ed5,0xbee2beed,0x3e713e44,0xbe15be44,0x3ef53eed,0xbec6bed5,0x3ea23e8e,0xbd49bdc8,0x3eff3efb,
0x3efb3f00,0xbdc80000,0xbdc80000,0xbefbbf00,0x3ed53eed,0xbe8ebe44,0xbe8ebe44,0xbed5beed,0x3e8e3eb5,0xbed5beb5,0xbed5beb5,0xbe8ebeb5,0x3dc83e44,0xbefbbeed,0xbefbbeed,0xbdc8be44,
0xbef5bf00,0x3e150000,0x3ee23eb5,0x3e713eb5,0xbea2bed5,0x3ec63e8e,0x3eff3efb,0xbd493dc8,0xbd49be44,0x3eff3eed,0x3ec63eed,0xbea2be44,0x3e713dc8,0x3ee23efb,0x3e153e8e,0xbef5bed5,
0x3eed3f00,0xbe440000,0xbeedbf00,0x3e440000,0x3e443eb5,0xbeedbeb5,0xbe44beb5,0x3eed3eb5,0xbe440000,0xbeedbf00,0x3e440000,0x3eed3f00,0xbeedbeb5,0xbe44beb5,0x3eed3eb5,0x3e443eb5,
0xbee2bf00,0x3e710000,0x3e153eb5,0xbef5beb5,0xbd49be8e,0x3eff3ed5,0xbea2bdc8,0xbec6befb,0x3ec63e44,0x3ea23eed,0xbeffbeed,0x3d49be44,0x3ef53efb,0xbe153dc8,0xbe71bed5,0x3ee23e8e,
0x3ed53f00,0xbe8e0000,0x3e8e0000,0x3ed53f00,0xbdc83e44,0xbefbbeed,0x3efb3eed,0xbdc83e44,0xbefbbeb5,0xbdc8beb5,0x3dc83eb5,0xbefbbeb5,0xbe8ebeed,0x3ed53e44,0xbed5be44,0xbe8ebeed,
0xbec6bf00,0x3ea20000,0xbeffbeb5,0xbd49beb5,0x3e71bdc8,0x3ee23efb,0xbe15bed5,0x3ef53e8e,0x3ef53eed,0xbe153e44,0x3ee23e44,0x3e713eed,0xbd493e8e,0xbeffbed5,0x3ea23efb,0xbec6bdc8,
0x3eb53f00,0xbeb50000,0x3eb53f00,0xbeb50000,0xbeb50000,0xbeb5bf00,0xbeb50000,0xbeb5bf00,0xbeb5bf00,0x3eb50000,0xbeb5bf00,0x3eb50000,0x3eb50000,0x3eb53f00,0x3eb50000,0x3eb53f00,
0xbea2bf00,0x3ec60000,0x3d49beb5,0x3eff3eb5,0x3ee23dc8,0x3e713efb,0x3ef53ed5,0xbe153e8e,0x3e153eed,0xbef5be44,0xbe713e44,0xbee2beed,0xbeffbe8e,0xbd49bed5,0xbec6befb,0x3ea2bdc8,
0x3e8e3f00,0xbed50000,0xbed50000,0xbe8ebf00,0xbefbbe44,0xbdc8beed,0xbdc8beed,0x3efb3e44,0x3dc8beb5,0x3efb3eb5,0x3efb3eb5,0xbdc83eb5,0x3ed53eed,0xbe8e3e44,0xbe8e3e44,0xbed5beed,
0xbe71bf00,0x3ee20000,0x3ef53eb5,0xbe153eb5,0x3eff3e8e,0xbd493ed5,0xbec63dc8,0xbea2befb,0xbea23e44,0xbec6beed,0xbd49beed,0x3eff3e44,0xbe15befb,0x3ef53dc8,0x3ee23ed5,0xbe713e8e,
0x3e443f00,0xbeed0000,0xbe44bf00,0x3eed0000,0xbeedbeb5,0x3e44beb5,0x3eed3eb5,0xbe443eb5,0x3eed0000,0x3e443f00,0xbeed0000,0xbe44bf00,0xbe443eb5,0xbeedbeb5,0x3e44beb5,0x3eed3eb5,
0xbe15bf00,0x3ef50000,0xbe713eb5,0xbee2beb5,0x3ec63ed5,0xbea23e8e,0xbd49befb,0x3eff3dc8,0xbeffbe44,0x3d49beed,0x3ea23eed,0xbec63e44,0x3ee2bdc8,0x3e713efb,0xbef5be8e,0x3e15bed5,
0x3dc83f00,0xbefb0000,0x3efb0000,0x3dc83f00,0xbe8ebeed,0x3ed5be44,0xbed53e44,0xbe8ebeed,0x3ed53eb5,0xbe8e3eb5,0x3e8ebeb5,0x3ed53eb5,0xbefbbe44,0x3dc8beed,0xbdc83eed,0xbefbbe44,
0xbd49bf00,0x3eff0000,0xbec6beb5,0x3ea2beb5,0x3e153efb,0xbef53dc8,0x3ee23e8e,0xbe713ed5,0xbe71beed,0x3ee2be44,0xbef5be44,0x3e15beed,0x3ea23ed5,0xbec63e8e,0x3eff3dc8,0xbd493efb,
0x3f00,0xbf000000,0x3f00,0xbf000000,0xbf00,0x3f000000,0xbf00,0x3f000000,0x3f00,0xbf000000,0x3f00,0xbf000000,0xbf00,0x3f000000,0xbf00,0x3f000000,
0x3d49bf00,0x3eff0000,0x3ec6beb5,0x3ea23eb5,0xbe153efb,0xbef5bdc8,0xbee23e8e,0xbe71bed5,0x3e71beed,0x3ee23e44,0x3ef5be44,0x3e153eed,0xbea23ed5,0xbec6be8e,0xbeff3dc8,0xbd49befb,
0xbdc83f00,0xbefb0000,0xbefb0000,0x3dc8bf00,0x3e8ebeed,0x3ed53e44,0x3ed53e44,0xbe8e3eed,0xbed53eb5,0xbe8ebeb5,0xbe8ebeb5,0x3ed5beb5,0x3efbbe44,0x3dc83eed,0x3dc83eed,0xbefb3e44,
0x3e15bf00,0x3ef50000,0x3e713eb5,0xbee23eb5,0xbec63ed5,0xbea2be8e,0x3d49befb,0x3effbdc8,0x3effbe44,0x3d493eed,0xbea23eed,0xbec6be44,0xbee2bdc8,0x3e71befb,0x3ef5be8e,0x3e153ed5,
0xbe443f00,0xbeed0000,0x3e44bf00,0x3eed0000,0x3eedbeb5,0x3e443eb5,0xbeed3eb5,0xbe44beb5,0xbeed0000,0x3e44bf00,0x3eed0000,0xbe443f00,0x3e443eb5,0xbeed3eb5,0xbe44beb5,0x3eedbeb5,
0x3e71bf00,0x3ee20000,0xbef53eb5,0xbe15beb5,0xbeff3e8e,0xbd49bed5,0x3ec63dc8,0xbea23efb,0x3ea23e44,0xbec63eed,0x3d49beed,0x3effbe44,0x3e15befb,0x3ef5bdc8,0xbee23ed5,0xbe71be8e,
0xbe8e3f00,0xbed50000,0x3ed50000,0xbe8e3f00,0x3efbbe44,0xbdc83eed,0x3dc8beed,0x3efbbe44,0xbdc8beb5,0x3efbbeb5,0xbefb3eb5,0xbdc8beb5,0xbed53eed,0xbe8ebe44,0x3e8e3e44,0xbed53eed,
0x3ea2bf00,0x3ec60000,0xbd49beb5,0x3effbeb5,0xbee23dc8,0x3e71befb,0xbef53ed5,0xbe15be8e,0xbe153eed,0xbef53e44,0x3e713e44,0xbee23eed,0x3effbe8e,0xbd493ed5,0x3ec6befb,0x3ea23dc8,
0xbeb53f00,0xbeb50000,0xbeb53f00,0xbeb50000,0x3eb50000,0xbeb53f00,0x3eb50000,0xbeb53f00,0x3eb5bf00,0x3eb50000,0x3eb5bf00,0x3eb50000,0xbeb50000,0x3eb5bf00,0xbeb50000,0x3eb5bf00,
0x3ec6bf00,0x3ea20000,0x3effbeb5,0xbd493eb5,0xbe71bdc8,0x3ee2befb,0x3e15bed5,0x3ef5be8e,0xbef53eed,0xbe15be44,0xbee23e44,0x3e71beed,0x3d493e8e,0xbeff3ed5,0xbea23efb,0xbec63dc8,
0xbed53f00,0xbe8e0000,0xbe8e0000,0x3ed5bf00,0x3dc83e44,0xbefb3eed,0xbefb3eed,0xbdc8be44,0x3efbbeb5,0xbdc83eb5,0xbdc83eb5,0xbefb3eb5,0x3e8ebeed,0x3ed5be44,0x3ed5be44,0xbe8e3eed,
0x3ee2bf00,0x3e710000,0xbe153eb5,0xbef53eb5,0x3d49be8e,0x3effbed5,0x3ea2bdc8,0xbec63efb,0xbec63e44,0x3ea2beed,0x3effbeed,0x3d493e44,0xbef53efb,0xbe15bdc8,0x3e71bed5,0x3ee2be8e,
0xbeed3f00,0xbe440000,0x3eedbf00,0x3e440000,0xbe443eb5,0xbeed3eb5,0x3e44beb5,0x3eedbeb5,0x3e440000,0xbeed3f00,0xbe440000,0x3eedbf00,0x3eedbeb5,0xbe443eb5,0xbeed3eb5,0x3e44beb5,
0x3ef5bf00,0x3e150000,0xbee23eb5,0x3e71beb5,0x3ea2bed5,0x3ec6be8e,0xbeff3efb,0xbd49bdc8,0x3d49be44,0x3effbeed,0xbec63eed,0xbea23e44,0xbe713dc8,0x3ee2befb,0xbe153e8e,0xbef53ed5,
0xbefb3f00,0xbdc80000,0x3dc80000,0xbefb3f00,0xbed53eed,0xbe8e3e44,0x3e8ebe44,0xbed53eed,0xbe8e3eb5,0xbed53eb5,0x3ed5beb5,0xbe8e3eb5,0xbdc83e44,0xbefb3eed,0x3efbbeed,0xbdc83e44,
0x3effbf00,0x3d490000,0x3ea2beb5,0x3ec6beb5,0x3ef5befb,0x3e15bdc8,0x3e71be8e,0x3ee2bed5,0x3ee2beed,0x3e71be44,0x3e15be44,0x3ef5beed,0x3ec6bed5,0x3ea2be8e,0x3d49bdc8,0x3effbefb,
0x3f003f00,0xbf003f00,0x3f003f00,0xbf003f00,0x3f003f00,0xbf003f00,0x3f003f00,0xbf003f00,0x3f003f00,0xbf003f00,0x3f003f00,0xbf003f00,0x3f003f00,0xbf003f00,0x3f003f00,0xbf003f00,
0x3d490000,0x3eff3f00,0x3ec63eb5,0x3ea23eb5,0x3e153dc8,0x3ef53efb,0x3ee23ed5,0x3e713e8e,0x3e713e44,0x3ee23eed,0x3ef53eed,0x3e153e44,0x3ea23e8e,0x3ec63ed5,0x3eff3efb,0x3d493dc8,
0xbefbbf00,0x3dc80000,0x3dc80000,0x3efb3f00,0xbed5beed,0x3e8e3e44,0x3e8e3e44,0x3ed53eed,0xbe8ebeb5,0x3ed53eb5,0x3ed53eb5,0x3e8e3eb5,0xbdc8be44,0x3efb3eed,0x3efb3eed,0x3dc83e44,
0xbe150000,0xbef5bf00,0xbe71beb5,0x3ee23eb5,0xbec6be8e,0xbea2bed5,0x3d49bdc8,0x3eff3efb,0xbeffbeed,0xbd49be44,0x3ea23e44,0x3ec63eed,0xbee2befb,0x3e713dc8,0x3ef53ed5,0x3e153e8e,
0x3eed3f00,0xbe440000,0xbeedbf00,0x3e440000,0x3e443eb5,0xbeedbeb5,0xbe44beb5,0x3eed3eb5,0xbe440000,0xbeedbf00,0x3e440000,0x3eed3f00,0xbeedbeb5,0xbe44beb5,0x3eed3eb5,0x3e443eb5,
0x3e710000,0x3ee23f00,0xbef5beb5,0xbe15beb5,0x3eff3ed5,0x3d493e8e,0xbec6befb,0x3ea23dc8,0x3ea23eed,0xbec6be44,0x3d49be44,0x3eff3eed,0xbe153dc8,0xbef5befb,0x3ee23e8e,0x3e713ed5,
0xbed5bf00,0x3e8e0000,0xbe8e0000,0xbed5bf00,0x3dc8be44,0x3efb3eed,0xbefbbeed,0x3dc8be44,0x3efb3eb5,0x3dc83eb5,0xbdc8beb5,0x3efb3eb5,0x3e8e3eed,0xbed5be44,0x3ed53e44,0x3e8e3eed,
0xbea20000,0xbec6bf00,0x3d493eb5,0xbeffbeb5,0xbee2befb,0x3e71bdc8,0xbef5be8e,0xbe15bed5,0x3e15be44,0x3ef53eed,0xbe71beed,0x3ee23e44,0x3eff3ed5,0xbd493e8e,0x3ec63dc8,0x3ea23efb,
0x3eb53f00,0xbeb50000,0x3eb53f00,0xbeb50000,0xbeb50000,0xbeb5bf00,0xbeb50000,0xbeb5bf00,0xbeb5bf00,0x3eb50000,0xbeb5bf00,0x3eb50000,0x3eb50000,0x3eb53f00,0x3eb50000,0x3eb53f00,
0x3ec60000,0x3ea23f00,0x3eff3eb5,0xbd493eb5,0x3e713efb,0xbee2bdc8,0xbe153e8e,0xbef5bed5,0xbef5be44,0xbe15beed,0xbee2beed,0x3e71be44,0xbd49bed5,0x3eff3e8e,0x3ea2bdc8,0x3ec63efb,
0xbe8ebf00,0x3ed50000,0x3ed50000,0x3e8e3f00,0x3efb3e44,0x3dc83eed,0x3dc83eed,0xbefbbe44,0xbdc83eb5,0xbefbbeb5,0xbefbbeb5,0x3dc8beb5,0xbed5beed,0x3e8ebe44,0x3e8ebe44,0x3ed53eed,
0xbee20000,0xbe71bf00,0x3e15beb5,0x3ef53eb5,0x3d49bed5,0x3eff3e8e,0x3ea23efb,0xbec63dc8,0x3ec63eed,0xbea23e44,0xbeffbe44,0xbd49beed,0xbef5bdc8,0xbe15befb,0x3e71be8e,0x3ee23ed5,
0x3e443f00,0xbeed0000,0xbe44bf00,0x3eed0000,0xbeedbeb5,0x3e44beb5,0x3eed3eb5,0xbe443eb5,0x3eed0000,0x3e443f00,0xbeed0000,0xbe44bf00,0xbe443eb5,0xbeedbeb5,0x3e44beb5,0x3eed3eb5,
0x3ef50000,0x3e153f00,0xbee2beb5,0x3e71beb5,0xbea23e8e,0xbec6bed5,0x3eff3dc8,0x3d493efb,0x3d49beed,0x3eff3e44,0xbec63e44,0xbea2beed,0x3e713efb,0xbee23dc8,0x3e15bed5,0x3ef53e8e,
0xbdc8bf00,0x3efb0000,0xbefb0000,0xbdc8bf00,0x3e8e3eed,0xbed53e44,0x3ed5be44,0x3e8e3eed,0xbed5beb5,0x3e8ebeb5,0xbe8e3eb5,0xbed5beb5,0x3efb3e44,0xbdc83eed,0x3dc8beed,0x3efb3e44,
0xbeff0000,0xbd49bf00,0xbea23eb5,0xbec6beb5,0x3ef5bdc8,0x3e153efb,0x3e71bed5,0x3ee23e8e,0xbee23e44,0xbe71beed,0xbe153eed,0xbef5be44,0x3ec6be8e,0x3ea23ed5,0x3d49befb,0x3eff3dc8,
0x3f00,0xbf000000,0x3f00,0xbf000000,0xbf00,0x3f000000,0xbf00,0x3f000000,0x3f00,0xbf000000,0x3f00,0xbf000000,0xbf00,0x3f000000,0xbf00,0x3f000000,
0x3eff0000,0xbd493f00,0x3ea23eb5,0xbec63eb5,0xbef5bdc8,0x3e15befb,0xbe71bed5,0x3ee2be8e,0x3ee23e44,0xbe713eed,0x3e153eed,0xbef53e44,0xbec6be8e,0x3ea2bed5,0xbd49befb,0x3effbdc8,
0x3dc8bf00,0x3efb0000,0x3efb0000,0xbdc83f00,0xbe8e3eed,0xbed5be44,0xbed5be44,0x3e8ebeed,0x3ed5beb5,0x3e8e3eb5,0x3e8e3eb5,0xbed53eb5,0xbefb3e44,0xbdc8beed,0xbdc8beed,0x3efbbe44,
0xbef50000,0x3e15bf00,0x3ee2beb5,0x3e713eb5,0x3ea23e8e,0xbec63ed5,0xbeff3dc8,0x3d49befb,0xbd49beed,0x3effbe44,0x3ec63e44,0xbea23eed,0xbe713efb,0xbee2bdc8,0xbe15bed5,0x3ef5be8e,
0xbe443f00,0xbeed0000,0x3e44bf00,0x3eed0000,0x3eedbeb5,0x3e443eb5,0xbeed3eb5,0xbe44beb5,0xbeed0000,0x3e44bf00,0x3eed0000,0xbe443f00,0x3e443eb5,0xbeed3eb5,0xbe44beb5,0x3eedbeb5,
0x3ee20000,0xbe713f00,0xbe15beb5,0x3ef5beb5,0xbd49bed5,0x3effbe8e,0xbea23efb,0xbec6bdc8,0xbec63eed,0xbea2be44,0x3effbe44,0xbd493eed,0x3ef5bdc8,0xbe153efb,0xbe71be8e,0x3ee2bed5,
0x3e8ebf00,0x3ed50000,0xbed50000,0x3e8ebf00,0xbefb3e44,0x3dc8beed,0xbdc83eed,0xbefb3e44,0x3dc83eb5,0xbefb3eb5,0x3efbbeb5,0x3dc83eb5,0x3ed5beed,0x3e8e3e44,0xbe8ebe44,0x3ed5beed,
0xbec60000,0x3ea2bf00,0xbeff3eb5,0xbd49beb5,0xbe713efb,0xbee23dc8,0x3e153e8e,0xbef53ed5,0x3ef5be44,0xbe153eed,0x3ee2beed,0x3e713e44,0x3d49bed5,0x3effbe8e,0xbea2bdc8,0x3ec6befb,
0xbeb53f00,0xbeb50000,0xbeb53f00,0xbeb50000,0x3eb50000,0xbeb53f00,0x3eb50000,0xbeb53f00,0x3eb5bf00,0x3eb50000,0x3eb5bf00,0x3eb50000,0xbeb50000,0x3eb5bf00,0xbeb50000,0x3eb5bf00,
0x3ea20000,0xbec63f00,0xbd493eb5,0xbeff3eb5,0x3ee2befb,0x3e713dc8,0x3ef5be8e,0xbe153ed5,0xbe15be44,0x3ef5beed,0x3e71beed,0x3ee2be44,0xbeff3ed5,0xbd49be8e,0xbec63dc8,0x3ea2befb,
0x3ed5bf00,0x3e8e0000,0x3e8e0000,0xbed53f00,0xbdc8be44,0x3efbbeed,0x3efbbeed,0x3dc83e44,0xbefb3eb5,0x3dc8beb5,0x3dc8beb5,0x3efbbeb5,0xbe8e3eed,0xbed53e44,0xbed53e44,0x3e8ebeed,
0xbe710000,0x3ee2bf00,0x3ef5beb5,0xbe153eb5,0xbeff3ed5,0x3d49be8e,0x3ec6befb,0x3ea2bdc8,0xbea23eed,0xbec63e44,0xbd49be44,0x3effbeed,0x3e153dc8,0xbef53efb,0xbee23e8e,0x3e71bed5,
0xbeed3f00,0xbe440000,0x3eedbf00,0x3e440000,0xbe443eb5,0xbeed3eb5,0x3e44beb5,0x3eedbeb5,0x3e440000,0xbeed3f00,0xbe440000,0x3eedbf00,0x3eedbeb5,0xbe443eb5,0xbeed3eb5,0x3e44beb5,
0x3e150000,0xbef53f00,0x3e71beb5,0x3ee2beb5,0x3ec6be8e,0xbea23ed5,0xbd49bdc8,0x3effbefb,0x3effbeed,0xbd493e44,0xbea23e44,0x3ec6beed,0x3ee2befb,0x3e71bdc8,0xbef53ed5,0x3e15be8e,
0x3efbbf00,0x3dc80000,0xbdc80000,0x3efbbf00,0x3ed5beed,0x3e8ebe44,0xbe8e3e44,0x3ed5beed,0x3e8ebeb5,0x3ed5beb5,0xbed53eb5,0x3e8ebeb5,0x3dc8be44,0x3efbbeed,0xbefb3eed,0x3dc8be44,
0xbd490000,0x3effbf00,0xbec63eb5,0x3ea2beb5,0xbe153dc8,0x3ef5befb,0xbee23ed5,0x3e71be8e,0xbe713e44,0x3ee2beed,0xbef53eed,0x3e15be44,0xbea23e8e,0x3ec6bed5,0xbeff3efb,0x3d49bdc8,
0x3f800000,0x0,0x3f800000,0x0,0x3f800000,0x0,0x3f800000,0x0,0x3f800000,0x0,0x3f800000,0x0,0x3f800000,0x0,0x3f800000,0x0,
0x3f800000,0x0,0x3f7ffec4,0xbbc90f88,0x3f7ffb11,0xbc490e90,0x3f7ff4e6,0xbc96c9b6,0x3f7fec43,0xbcc90ab0,0x3f7fe129,0xbcfb49ba,0x3f7fd397,0xbd16c32c,0x3f7fc38f,0xbd2fe007,
0x3f800000,0x0,0x3f7ffb11,0xbc490e90,0x3f7fec43,0xbcc90ab0,0x3f7fd397,0xbd16c32c,0x3f7fb10f,0xbd48fb30,0x3f7f84ab,0xbd7b2b74,0x3f7f4e6d,0xbd96a905,0x3f7f0e58,0xbdafb680,
0x3f800000,0x0,0x3f7ff4e6,0xbc96c9b6,0x3f7fd397,0xbd16c32c,0x3f7f9c18,0xbd621469,0x3f7f4e6d,0xbd96a905,0x3f7eea9d,0xbdbc3ac3,0x3f7e70b0,0xbde1bc2e,0x3f7de0b1,0xbe039502,
0x3f800000,0x0,0x3f7fec43,0xbcc90ab0,0x3f7fb10f,0xbd48fb30,0x3f7f4e6d,0xbd96a905,0x3f7ec46d,0xbdc8bd36,0x3f7e1324,0xbdfab273,0x3f7d3aac,0xbe164083,0x3f7c3b28,0xbe2f10a2,
0x3f800000,0x0,0x3f7fe129,0xbcfb49ba,0x3f7f84ab,0xbd7b2b74,0x3f7eea9d,0xbdbc3ac3,0x3f7e1324,0xbdfab273,0x3f7cfe73,0xbe1c76de,0x3f7baccd,0xbe3b6ecf,0x3f7a1e84,0xbe5a3997,
0x3f800000,0x0,0x3f7fd397,0xbd16c32c,0x3f7f4e6d,0xbd96a905,0x3f7e70b0,0xbde1bc2e,0x3f7d3aac,0xbe164083,0x3f7baccd,0xbe3b6ecf,0x3f79c79d,0xbe605c13,0x3f778bc5,0xbe827dc0,
0x3f800000,0x0,0x3f7fc38f,0xbd2fe007,0x3f7f0e58,0xbdafb680,0x3f7de0b1,0xbe039502,0x3f7c3b28,0xbe2f10a2,0x3f7a1e84,0xbe5a3997,0x3f778bc5,0xbe827dc0,0x3f748422,0xbe97a117,
0x3f800000,0x0,0x3f7fb10f,0xbd48fb30,0x3f7ec46d,0xbdc8bd36,0x3f7d3aac,0xbe164083,0x3f7b14be,0xbe47c5c2,0x3f7853f8,0xbe78cfcc,0x3f74fa0b,0xbe94a031,0x3f710908,0xbeac7cd4,
0x3f800000,0x0,0x3f7f9c18,0xbd621469,0x3f7e70b0,0xbde1bc2e,0x3f7c7eb0,0xbe28defc,0x3f79c79d,0xbe605c13,0x3f764d97,0xbe8b9507,0x3f721352,0xbea68f12,0x3f6d1c1d,0xbec1071e,
0x3f800000,0x0,0x3f7f84ab,0xbd7b2b74,0x3f7e1324,0xbdfab273,0x3f7baccd,0xbe3b6ecf,0x3f7853f8,0xbe78cfcc,0x3f740bdd,0xbe9aa086,0x3f6ed89e,0xbeb8442a,0x3f68bf3c,0xbed53641,
0x3f800000,0x0,0x3f7f6ac7,0xbd8a200a,0x3f7dabcc,0xbe09cf86,0x3f7ac516,0xbe4dee60,0x3f76ba07,0xbe888e93,0x3f718f57,0xbea986c4,0x3f6b4b0c,0xbec9b953,0x3f63f473,0xbee900b7,
0x3f800000,0x0,0x3f7f4e6d,0xbd96a905,0x3f7d3aac,0xbe164083,0x3f79c79d,0xbe605c13,0x3f74fa0b,0xbe94a031,0x3f6ed89e,0xbeb8442a,0x3f676bd8,0xbedae880,0x3f5ebe05,0xbefc5d27,
0x3f800000,0x0,0x3f7f2f9d,0xbda3308c,0x3f7cbfc9,0xbe22abb6,0x3f78b47b,0xbe72b651,0x3f731447,0xbea09ae5,0x3f6be858,0xbec6d529,0x3f633c5a,0xbeebcbbb,0x3f591e6a,0xbf07a136,
0x3f800000,0x0,0x3f7f0e58,0xbdafb680,0x3f7c3b28,0xbe2f10a2,0x3f778bc5,0xbe827dc0,0x3f710908,0xbeac7cd4,0x3f68bf3c,0xbed53641,0x3f5ebe05,0xbefc5d27,0x3f531849,0xbf10d3cd,
0x3f800000,0x0,0x3f7eea9d,0xbdbc3ac3,0x3f7baccd,0xbe3b6ecf,0x3f764d97,0xbe8b9507,0x3f6ed89e,0xbeb8442a,0x3f655e0b,0xbee363fa,0x3f59f26a,0xbf064b82,0x3f4cae79,0xbf19c200,
0x3f800000,0x0,0x3f7ec46d,0xbdc8bd36,0x3f7b14be,0xbe47c5c2,0x3f74fa0b,0xbe94a031,0x3f6c835e,0xbec3ef15,0x3f61c598,0xbef15aea,0x3f54db31,0xbf0e39da,0x3f45e403,0xbf226799,
0x3f800000,0x0,0x3f7e9bc9,0xbdd53db9,0x3f7a7302,0xbe541501,0x3f73913f,0xbe9d9e78,0x3f6a09a7,0xbecf7bca,0x3f5df6be,0xbeff17b2,0x3f4f7a1f,0xbf15f6d9,0x3f3ebc1b,0xbf2ac082,
0x3f800000,0x0,0x3f7e70b0,0xbde1bc2e,0x3f79c79d,0xbe605c13,0x3f721352,0xbea68f12,0x3f676bd8,0xbedae880,0x3f59f26a,0xbf064b82,0x3f49d112,0xbf1d7fd1,0x3f373a23,0xbf32c8c9,
0x3f800000,0x0,0x3f7e4323,0xbdee3876,0x3f791298,0xbe6c9a7f,0x3f708066,0xbeaf713a,0x3f64aa59,0xbee63375,0x3f55b993,0xbf0cead0,0x3f43e200,0xbf24d225,0x3f2f61a5,0xbf3a7ca4,
0x3f800000,0x0,0x3f7e1324,0xbdfab273,0x3f7853f8,0xbe78cfcc,0x3f6ed89e,0xbeb8442a,0x3f61c598,0xbef15aea,0x3f514d3d,0xbf13682a,0x3f3daef9,0xbf2beb4a,0x3f273656,0xbf41d870,
0x3f800000,0x0,0x3f7de0b1,0xbe039502,0x3f778bc5,0xbe827dc0,0x3f6d1c1d,0xbec1071e,0x3f5ebe05,0xbefc5d27,0x3f4cae79,0xbf19c200,0x3f373a23,0xbf32c8c9,0x3f1ebc12,0xbf48d8b3,
0x3f800000,0x0,0x3f7dabcc,0xbe09cf86,0x3f76ba07,0xbe888e93,0x3f6b4b0c,0xbec9b953,0x3f5b941a,0xbf039c3d,0x3f47de65,0xbf1ff6cb,0x3f3085bb,0xbf396842,0x3f15f6d9,0xbf4f7a1f,
0x3f800000,0x0,0x3f7d7474,0xbe1008b7,0x3f75dec6,0xbe8e9a22,0x3f696591,0xbed25a09,0x3f584853,0xbf08f59b,0x3f42de29,0xbf26050a,0x3f299415,0xbf3fc767,0x3f0cead0,0xbf55b993,
0x3f800000,0x0,0x3f7d3aac,0xbe164083,0x3f74fa0b,0xbe94a031,0x3f676bd8,0xbedae880,0x3f54db31,0xbf0e39da,0x3f3daef9,0xbf2beb4a,0x3f226799,0xbf45e403,0x3f039c3d,0xbf5b941a,
0x3f800000,0x0,0x3f7cfe73,0xbe1c76de,0x3f740bdd,0xbe9aa086,0x3f655e0b,0xbee363fa,0x3f514d3d,0xbf13682a,0x3f385216,0xbf31a81d,0x3f1b02c6,0xbf4bbbf8,0x3ef41f07,0xbf6106f2,
0x3f800000,0x0,0x3f7cbfc9,0xbe22abb6,0x3f731447,0xbea09ae5,0x3f633c5a,0xbeebcbbb,0x3f4d9f02,0xbf187fc0,0x3f32c8c9,0xbf373a23,0x3f13682a,0xbf514d3d,0x3ee0924f,0xbf660f88,
0x3f800000,0x0,0x3f7c7eb0,0xbe28defc,0x3f721352,0xbea68f12,0x3f6106f2,0xbef41f07,0x3f49d112,0xbf1d7fd1,0x3f2d1469,0xbf3ca003,0x3f0b9a6b,0xbf5695e5,0x3ecc9b8b,0xbf6aab7b,
0x3f800000,0x0,0x3f7c3b28,0xbe2f10a2,0x3f710908,0xbeac7cd4,0x3f5ebe05,0xbefc5d27,0x3f45e403,0xbf226799,0x3f273656,0xbf41d870,0x3f039c3d,0xbf5b941a,0x3eb8442a,0xbf6ed89e,
0x3f800000,0x0,0x3f7bf531,0xbe354098,0x3f6ff573,0xbeb263ef,0x3f5c61c7,0xbf0242b1,0x3f41d870,0xbf273656,0x3f212ff9,0xbf46e22a,0x3ef6e0cb,0xbf604621,0x3ea395c5,0xbf7294f8,
0x3f800000,0x0,0x3f7baccd,0xbe3b6ecf,0x3f6ed89e,0xbeb8442a,0x3f59f26a,0xbf064b82,0x3f3daef9,0xbf2beb4a,0x3f1b02c6,0xbf4bbbf8,0x3ee63375,0xbf64aa59,0x3e8e9a22,0xbf75dec6,
0x3f800000,0x0,0x3f7b61fc,0xbe419b37,0x3f6db293,0xbebe1d4a,0x3f577026,0xbf0a48ad,0x3f396842,0xbf3085bb,0x3f14b039,0xbf5064af,0x3ed53641,0xbf68bf3c,0x3e72b651,0xbf78b47b,
0x3f800000,0x0,0x3f800000,0x0,0x3f800000,0x0,0x3f800000,0x0,0x3f800000,0x0,0x3f800000,0x0,0x3f800000,0x0,0x3f800000,0x0,
0x3f7fb10f,0xbd48fb30,0x3f7f9c18,0xbd621469,0x3f7f84ab,0xbd7b2b74,0x3f7f6ac7,0xbd8a200a,0x3f7f4e6d,0xbd96a905,0x3f7f2f9d,0xbda3308c,0x3f7f0e58,0xbdafb680,0x3f7eea9d,0xbdbc3ac3,
0x3f7ec46d,0xbdc8bd36,0x3f7e70b0,0xbde1bc2e,0x3f7e1324,0xbdfab273,0x3f7dabcc,0xbe09cf86,0x3f7d3aac,0xbe164083,0x3f7cbfc9,0xbe22abb6,0x3f7c3b28,0xbe2f10a2,0x3f7baccd,0xbe3b6ecf,
0x3f7d3aac,0xbe164083,0x3f7c7eb0,0xbe28defc,0x3f7baccd,0xbe3b6ecf,0x3f7ac516,0xbe4dee60,0x3f79c79d,0xbe605c13,0x3f78b47b,0xbe72b651,0x3f778bc5,0xbe827dc0,0x3f764d97,0xbe8b9507,
0x3f7b14be,0xbe47c5c2,0x3f79c79d,0xbe605c13,0x3f7853f8,0xbe78cfcc,0x3f76ba07,0xbe888e93,0x3f74fa0b,0xbe94a031,0x3f731447,0xbea09ae5,0x3f710908,0xbeac7cd4,0x3f6ed89e,0xbeb8442a,
0x3f7853f8,0xbe78cfcc,0x3f764d97,0xbe8b9507,0x3f740bdd,0xbe9aa086,0x3f718f57,0xbea986c4,0x3f6ed89e,0xbeb8442a,0x3f6be858,0xbec6d529,0x3f68bf3c,0xbed53641,0x3f655e0b,0xbee363fa,
0x3f74fa0b,0xbe94a031,0x3f721352,0xbea68f12,0x3f6ed89e,0xbeb8442a,0x3f6b4b0c,0xbec9b953,0x3f676bd8,0xbedae880,0x3f633c5a,0xbeebcbbb,0x3f5ebe05,0xbefc5d27,0x3f59f26a,0xbf064b82,
0x3f710908,0xbeac7cd4,0x3f6d1c1d,0xbec1071e,0x3f68bf3c,0xbed53641,0x3f63f473,0xbee900b7,0x3f5ebe05,0xbefc5d27,0x3f591e6a,0xbf07a136,0x3f531849,0xbf10d3cd,0x3f4cae79,0xbf19c200,
0x3f6c835e,0xbec3ef15,0x3f676bd8,0xbedae880,0x3f61c598,0xbef15aea,0x3f5b941a,0xbf039c3d,0x3f54db31,0xbf0e39da,0x3f4d9f02,0xbf187fc0,0x3f45e403,0xbf226799,0x3f3daef9,0xbf2beb4a,
0x3f676bd8,0xbedae880,0x3f6106f2,0xbef41f07,0x3f59f26a,0xbf064b82,0x3f5233c6,0xbf121eb0,0x3f49d112,0xbf1d7fd1,0x3f40d0da,0xbf286605,0x3f373a23,0xbf32c8c9,0x3f2d1469,0xbf3ca003,
0x3f61c598,0xbef15aea,0x3f59f26a,0xbf064b82,0x3f514d3d,0xbf13682a,0x3f47de65,0xbf1ff6cb,0x3f3daef9,0xbf2beb4a,0x3f32c8c9,0xbf373a23,0x3f273656,0xbf41d870,0x3f1b02c6,0xbf4bbbf8,
0x3f5b941a,0xbf039c3d,0x3f5233c6,0xbf121eb0,0x3f47de65,0xbf1ff6cb,0x3f3ca003,0xbf2d1469,0x3f3085bb,0xbf396842,0x3f239da9,0xbf44e3f5,0x3f15f6d9,0xbf4f7a1f,0x3f07a136,0xbf591e6a,
0x3f54db31,0xbf0e39da,0x3f49d112,0xbf1d7fd1,0x3f3daef9,0xbf2beb4a,0x3f3085bb,0xbf396842,0x3f226799,0xbf45e403,0x3f13682a,0xbf514d3d,0x3f039c3d,0xbf5b941a,0x3ee63375,0xbf64aa59,
0x3f4d9f02,0xbf187fc0,0x3f40d0da,0xbf286605,0x3f32c8c9,0xbf373a23,0x3f239da9,0xbf44e3f5,0x3f13682a,0xbf514d3d,0x3f0242b1,0xbf5c61c7,0x3ee0924f,0xbf660f88,0x3ebb31a0,0xbf6e46be,
0x3f45e403,0xbf226799,0x3f373a23,0xbf32c8c9,0x3f273656,0xbf41d870,0x3f15f6d9,0xbf4f7a1f,0x3f039c3d,0xbf5b941a,0x3ee0924f,0xbf660f88,0x3eb8442a,0xbf6ed89e,0x3e8e9a22,0xbf75dec6,
0x3f3daef9,0xbf2beb4a,0x3f2d1469,0xbf3ca003,0x3f1b02c6,0xbf4bbbf8,0x3f07a136,0xbf591e6a,0x3ee63375,0xbf64aa59,0x3ebb31a0,0xbf6e46be,0x3e8e9a22,0xbf75dec6,0x3e419b37,0xbf7b61fc,
0x3f3504f3,0xbf3504f3,0x3f226799,0xbf45e403,0x3f0e39da,0xbf54db31,0x3ef15aea,0xbf61c598,0x3ec3ef15,0xbf6c835e,0x3e94a031,0xbf74fa0b,0x3e47c5c2,0xbf7b14be,0x3dc8bd36,0xbf7ec46d,
0x3f2beb4a,0xbf3daef9,0x3f173c07,0xbf4e8d90,0x3f00e7e4,0xbf5d2d53,0x3ed25a09,0xbf696591,0x3ea09ae5,0xbf731447,0x3e5a3997,0xbf7a1e84,0x3de1bc2e,0xbf7e70b0,0x3bc90f88,0xbf7ffec4,
0x3f226799,0xbf45e403,0x3f0b9a6b,0xbf5695e5,0x3ee63375,0xbf64aa59,0x3eb263ef,0xbf6ff573,0x3e78cfcc,0xbf7853f8,0x3e09cf86,0xbf7dabcc,0x3cc90ab0,0xbf7fec43,0xbdafb680,0xbf7f0e58,
0x3f187fc0,0xbf4d9f02,0x3eff17b2,0xbf5df6be,0x3ec9b953,0xbf6b4b0c,0x3e919ddd,0xbf756d97,0x3e2f10a2,0xbf7c3b28,0x3d621469,0xbf7f9c18,0xbd7b2b74,0xbf7f84ab,0xbe354098,0xbf7bf531,
0x3f0e39da,0xbf54db31,0x3ee63375,0xbf64aa59,0x3eac7cd4,0xbf710908,0x3e605c13,0xbf79c79d,0x3dc8bd36,0xbf7ec46d,0xbcc90ab0,0xbf7fec43,0xbe164083,0xbf7d3aac,0xbe888e93,0xbf76ba07,
0x3f039c3d,0xbf5b941a,0x3ecc9b8b,0xbf6aab7b,0x3e8e9a22,0xbf75dec6,0x3e1c76de,0xbf7cfe73,0x3cc90ab0,0xbf7fec43,0xbdd53db9,0xbf7e9bc9,0xbe6c9a7f,0xbf791298,0xbeb554ec,0xbf6f6830,
0x3ef15aea,0xbf61c598,0x3eb263ef,0xbf6ff573,0x3e605c13,0xbf79c79d,0x3dafb680,0xbf7f0e58,0xbd48fb30,0xbf7fb10f,0xbe3b6ecf,0xbf7baccd,0xbea09ae5,0xbf731447,0xbee0924f,0xbf660f88,
0x3edae880,0xbf676bd8,0x3e97a117,0xbf748422,0x3e22abb6,0xbf7cbfc9,0x3c96c9b6,0xbf7ff4e6,0xbdfab273,0xbf7e1324,0xbe8586ce,0xbf772417,0xbec9b953,0xbf6b4b0c,0xbf04f484,0xbf5ac450,
0x3ec3ef15,0xbf6c835e,0x3e78cfcc,0xbf7853f8,0x3dc8bd36,0xbf7ec46d,0xbd48fb30,0xbf7fb10f,0xbe47c5c2,0xbf7b14be,0xbeac7cd4,0xbf710908,0xbef15aea,0xbf61c598,0xbf187fc0,0xbf4d9f02,
0x3eac7cd4,0xbf710908,0x3e419b37,0xbf7b61fc,0x3d16c32c,0xbf7fd397,0xbdee3876,0xbf7e4323,0xbe888e93,0xbf76ba07,0xbed25a09,0xbf696591,0xbf0b9a6b,0xbf5695e5,0xbf2ac082,0xbf3ebc1b,
0x3e94a031,0xbf74fa0b,0x3e09cf86,0xbf7dabcc,0xbcc90ab0,0xbf7fec43,0xbe3b6ecf,0xbf7baccd,0xbeac7cd4,0xbf710908,0xbef6e0cb,0xbf604621,0xbf1d7fd1,0xbf49d112,0xbf3b8f3b,0xbf2e3bde,
0x3e78cfcc,0xbf7853f8,0x3da3308c,0xbf7f2f9d,0xbdafb680,0xbf7f0e58,0xbe7ee6e1,0xbf77f110,0xbecf7bca,0xbf6a09a7,0xbf0cead0,0xbf55b993,0xbf2e3bde,0xbf3b8f3b,0xbf4ac77f,0xbf1c420c,
0x3e47c5c2,0xbf7b14be,0x3cc90ab0,0xbf7fec43,0xbe164083,0xbf7d3aac,0xbea09ae5,0xbf731447,0xbef15aea,0xbf61c598,0xbf1d7fd1,0xbf49d112,0xbf3daef9,0xbf2beb4a,0xbf584853,0xbf08f59b,
0x3e164083,0xbf7d3aac,0xbcfb49ba,0xbf7fe129,0xbe541501,0xbf7a7302,0xbec1071e,0xbf6d1c1d,0xbf08f59b,0xbf584853,0xbf2d1469,0xbf3ca003,0xbf4bbbf8,0xbf1b02c6,0xbf63f473,0xbee900b7,
0x3dc8bd36,0xbf7ec46d,0xbdafb680,0xbf7f0e58,0xbe888e93,0xbf76ba07,0xbee0924f,0xbf660f88,0xbf187fc0,0xbf4d9f02,0xbf3b8f3b,0xbf2e3bde,0xbf584853,0xbf08f59b,0xbf6db293,0xbebe1d4a,
0x3d48fb30,0xbf7fb10f,0xbe1008b7,0xbf7d7474,0xbea68f12,0xbf721352,0xbeff17b2,0xbf5df6be,0xbf273656,0xbf41d870,0xbf48d8b3,0xbf1ebc12,0xbf633c5a,0xbeebcbbb,0xbf756d97,0xbe919ddd,
0x3f800000,0x0,0x3f800000,0x0,0x3f800000,0x0,0x3f800000,0x0,0x3f800000,0x0,0x3f800000,0x0,0x3f800000,0x0,0x3f800000,0x0,
0x3f7ec46d,0xbdc8bd36,0x3f7e9bc9,0xbdd53db9,0x3f7e70b0,0xbde1bc2e,0x3f7e4323,0xbdee3876,0x3f7e1324,0xbdfab273,0x3f7de0b1,0xbe039502,0x3f7dabcc,0xbe09cf86,0x3f7d7474,0xbe1008b7,
0x3f7b14be,0xbe47c5c2,0x3f7a7302,0xbe541501,0x3f79c79d,0xbe605c13,0x3f791298,0xbe6c9a7f,0x3f7853f8,0xbe78cfcc,0x3f778bc5,0xbe827dc0,0x3f76ba07,0xbe888e93,0x3f75dec6,0xbe8e9a22,
0x3f74fa0b,0xbe94a031,0x3f73913f,0xbe9d9e78,0x3f721352,0xbea68f12,0x3f708066,0xbeaf713a,0x3f6ed89e,0xbeb8442a,0x3f6d1c1d,0xbec1071e,0x3f6b4b0c,0xbec9b953,0x3f696591,0xbed25a09,
0x3f6c835e,0xbec3ef15,0x3f6a09a7,0xbecf7bca,0x3f676bd8,0xbedae880,0x3f64aa59,0xbee63375,0x3f61c598,0xbef15aea,0x3f5ebe05,0xbefc5d27,0x3f5b941a,0xbf039c3d,0x3f584853,0xbf08f59b,
0x3f61c598,0xbef15aea,0x3f5df6be,0xbeff17b2,0x3f59f26a,0xbf064b82,0x3f55b993,0xbf0cead0,0x3f514d3d,0xbf13682a,0x3f4cae79,0xbf19c200,0x3f47de65,0xbf1ff6cb,0x3f42de29,0xbf26050a,
0x3f54db31,0xbf0e39da,0x3f4f7a1f,0xbf15f6d9,0x3f49d112,0xbf1d7fd1,0x3f43e200,0xbf24d225,0x3f3daef9,0xbf2beb4a,0x3f373a23,0xbf32c8c9,0x3f3085bb,0xbf396842,0x3f299415,0xbf3fc767,
0x3f45e403,0xbf226799,0x3f3ebc1b,0xbf2ac082,0x3f373a23,0xbf32c8c9,0x3f2f61a5,0xbf3a7ca4,0x3f273656,0xbf41d870,0x3f1ebc12,0xbf48d8b3,0x3f15f6d9,0xbf4f7a1f,0x3f0cead0,0xbf55b993,
0x3f3504f3,0xbf3504f3,0x3f2beb4a,0xbf3daef9,0x3f226799,0xbf45e403,0x3f187fc0,0xbf4d9f02,0x3f0e39da,0xbf54db31,0x3f039c3d,0xbf5b941a,0x3ef15aea,0xbf61c598,0x3edae880,0xbf676bd8,
0x3f226799,0xbf45e403,0x3f173c07,0xbf4e8d90,0x3f0b9a6b,0xbf5695e5,0x3eff17b2,0xbf5df6be,0x3ee63375,0xbf64aa59,0x3ecc9b8b,0xbf6aab7b,0x3eb263ef,0xbf6ff573,0x3e97a117,0xbf748422,
0x3f0e39da,0xbf54db31,0x3f00e7e4,0xbf5d2d53,0x3ee63375,0xbf64aa59,0x3ec9b953,0xbf6b4b0c,0x3eac7cd4,0xbf710908,0x3e8e9a22,0xbf75dec6,0x3e605c13,0xbf79c79d,0x3e22abb6,0xbf7cbfc9,
0x3ef15aea,0xbf61c598,0x3ed25a09,0xbf696591,0x3eb263ef,0xbf6ff573,0x3e919ddd,0xbf756d97,0x3e605c13,0xbf79c79d,0x3e1c76de,0xbf7cfe73,0x3dafb680,0xbf7f0e58,0x3c96c9b6,0xbf7ff4e6,
0x3ec3ef15,0xbf6c835e,0x3ea09ae5,0xbf731447,0x3e78cfcc,0xbf7853f8,0x3e2f10a2,0xbf7c3b28,0x3dc8bd36,0xbf7ec46d,0x3cc90ab0,0xbf7fec43,0xbd48fb30,0xbf7fb10f,0xbdfab273,0xbf7e1324,
0x3e94a031,0xbf74fa0b,0x3e5a3997,0xbf7a1e84,0x3e09cf86,0xbf7dabcc,0x3d621469,0xbf7f9c18,0xbcc90ab0,0xbf7fec43,0xbdd53db9,0xbf7e9bc9,0xbe3b6ecf,0xbf7baccd,0xbe8586ce,0xbf772417,
0x3e47c5c2,0xbf7b14be,0x3de1bc2e,0xbf7e70b0,0x3cc90ab0,0xbf7fec43,0xbd7b2b74,0xbf7f84ab,0xbe164083,0xbf7d3aac,0xbe6c9a7f,0xbf791298,0xbea09ae5,0xbf731447,0xbec9b953,0xbf6b4b0c,
0x3dc8bd36,0xbf7ec46d,0x3bc90f88,0xbf7ffec4,0xbdafb680,0xbf7f0e58,0xbe354098,0xbf7bf531,0xbe888e93,0xbf76ba07,0xbeb554ec,0xbf6f6830,0xbee0924f,0xbf660f88,0xbf04f484,0xbf5ac450,
0x0,0xbf800000,0xbdc8bd36,0xbf7ec46d,0xbe47c5c2,0xbf7b14be,0xbe94a031,0xbf74fa0b,0xbec3ef15,0xbf6c835e,0xbef15aea,0xbf61c598,0xbf0e39da,0xbf54db31,0xbf226799,0xbf45e403,
0xbdc8bd36,0xbf7ec46d,0xbe4dee60,0xbf7ac516,0xbe9aa086,0xbf740bdd,0xbecc9b8b,0xbf6aab7b,0xbefc5d27,0xbf5ebe05,0xbf14b039,0xbf5064af,0xbf299415,0xbf3fc767,0xbf3ca003,0xbf2d1469,
0xbe47c5c2,0xbf7b14be,0xbe9aa086,0xbf740bdd,0xbecf7bca,0xbf6a09a7,0xbf00e7e4,0xbf5d2d53,0xbf187fc0,0xbf4d9f02,0xbf2e3bde,0xbf3b8f3b,0xbf41d870,0xbf273656,0xbf531849,0xbf10d3cd,
0xbe94a031,0xbf74fa0b,0xbecc9b8b,0xbf6aab7b,0xbf00e7e4,0xbf5d2d53,0xbf19c200,0xbf4cae79,0xbf3085bb,0xbf396842,0xbf44e3f5,0xbf239da9,0xbf5695e5,0xbf0b9a6b,0xbf655e0b,0xbee363fa,
0xbec3ef15,0xbf6c835e,0xbefc5d27,0xbf5ebe05,0xbf187fc0,0xbf4d9f02,0xbf3085bb,0xbf396842,0xbf45e403,0xbf226799,0xbf584853,0xbf08f59b,0xbf676bd8,0xbedae880,0xbf731447,0xbea09ae5,
0xbef15aea,0xbf61c598,0xbf14b039,0xbf5064af,0xbf2e3bde,0xbf3b8f3b,0xbf44e3f5,0xbf239da9,0xbf584853,0xbf08f59b,0xbf6816a8,0xbed8106b,0xbf740bdd,0xbe9aa086,0xbf7bf531,0xbe354098,
0xbf0e39da,0xbf54db31,0xbf299415,0xbf3fc767,0xbf41d870,0xbf273656,0xbf5695e5,0xbf0b9a6b,0xbf676bd8,0xbedae880,0xbf740bdd,0xbe9aa086,0xbf7c3b28,0xbe2f10a2,0xbf7fd397,0xbd16c32c,
0xbf226799,0xbf45e403,0xbf3ca003,0xbf2d1469,0xbf531849,0xbf10d3cd,0xbf655e0b,0xbee363fa,0xbf731447,0xbea09ae5,0xbf7bf531,0xbe354098,0xbf7fd397,0xbd16c32c,0xbf7e9bc9,0x3dd53db9,
0xbf3504f3,0xbf3504f3,0xbf4d9f02,0xbf187fc0,0xbf61c598,0xbef15aea,0xbf710908,0xbeac7cd4,0xbf7b14be,0xbe47c5c2,0xbf7fb10f,0xbd48fb30,0xbf7ec46d,0x3dc8bd36,0xbf7853f8,0x3e78cfcc,
0xbf45e403,0xbf226799,0xbf5c61c7,0xbf0242b1,0xbf6db293,0xbebe1d4a,0xbf796e4e,0xbe667c66,0xbf7f4e6d,0xbd96a905,0xbf7f2f9d,0x3da3308c,0xbf791298,0x3e6c9a7f,0xbf6d1c1d,0x3ec1071e,
0xbf54db31,0xbf0e39da,0xbf68bf3c,0xbed53641,0xbf76ba07,0xbe888e93,0xbf7e70b0,0xbde1bc2e,0xbf7fb10f,0x3d48fb30,0xbf7a7302,0x3e541501,0xbf6ed89e,0x3eb8442a,0xbf5d2d53,0x3f00e7e4,
0xbf61c598,0xbef15aea,0xbf7294f8,0xbea395c5,0xbf7cbfc9,0xbe22abb6,0xbf7ffec4,0x3bc90f88,0xbf7c3b28,0x3e2f10a2,0xbf718f57,0x3ea986c4,0xbf604621,0x3ef6e0cb,0xbf48d8b3,0x3f1ebc12,
0xbf6c835e,0xbec3ef15,0xbf79c79d,0xbe605c13,0xbf7fb10f,0xbd48fb30,0xbf7e1324,0x3dfab273,0xbf74fa0b,0x3e94a031,0xbf64aa59,0x3ee63375,0xbf4d9f02,0x3f187fc0,0xbf3085bb,0x3f396842,
0xbf74fa0b,0xbe94a031,0xbf7e4323,0xbdee3876,0xbf7f84ab,0x3d7b2b74,0xbf78b47b,0x3e72b651,0xbf6a09a7,0x3ecf7bca,0xbf53fac3,0x3f0f8784,0xbf373a23,0x3f32c8c9,0xbf14b039,0x3f5064af,
0xbf7b14be,0xbe47c5c2,0xbf7ffb11,0xbc490e90,0xbf7c3b28,0x3e2f10a2,0xbf6ff573,0x3eb263ef,0xbf5b941a,0x3f039c3d,0xbf3fc767,0x3f299415,0xbf1d7fd1,0x3f49d112,0xbeebcbbb,0x3f633c5a,
0xbf7ec46d,0xbdc8bd36,0xbf7eea9d,0x3dbc3ac3,0xbf75dec6,0x3e8e9a22,0xbf63f473,0x3ee900b7,0xbf49d112,0x3f1d7fd1,0xbf286605,0x3f40d0da,0xbf00e7e4,0x3f5d2d53,0xbea986c4,0x3f718f57,
0x3f800000,0x0,0x3f800000,0x0,0x3f800000,0x0,0x3f800000,0x0,0x3f800000,0x0,0x3f800000,0x0,0x3f800000,0x0,0x3f800000,0x0,
0x3f7d3aac,0xbe164083,0x3f7cfe73,0xbe1c76de,0x3f7cbfc9,0xbe22abb6,0x3f7c7eb0,0xbe28defc,0x3f7c3b28,0xbe2f10a2,0x3f7bf531,0xbe354098,0x3f7baccd,0xbe3b6ecf,0x3f7b61fc,0xbe419b37,
0x3f74fa0b,0xbe94a031,0x3f740bdd,0xbe9aa086,0x3f731447,0xbea09ae5,0x3f721352,0xbea68f12,0x3f710908,0xbeac7cd4,0x3f6ff573,0xbeb263ef,0x3f6ed89e,0xbeb8442a,0x3f6db293,0xbebe1d4a,
0x3f676bd8,0xbedae880,0x3f655e0b,0xbee363fa,0x3f633c5a,0xbeebcbbb,0x3f6106f2,0xbef41f07,0x3f5ebe05,0xbefc5d27,0x3f5c61c7,0xbf0242b1,0x3f59f26a,0xbf064b82,0x3f577026,0xbf0a48ad,
0x3f54db31,0xbf0e39da,0x3f514d3d,0xbf13682a,0x3f4d9f02,0xbf187fc0,0x3f49d112,0xbf1d7fd1,0x3f45e403,0xbf226799,0x3f41d870,0xbf273656,0x3f3daef9,0xbf2beb4a,0x3f396842,0xbf3085bb,
0x3f3daef9,0xbf2beb4a,0x3f385216,0xbf31a81d,0x3f32c8c9,0xbf373a23,0x3f2d1469,0xbf3ca003,0x3f273656,0xbf41d870,0x3f212ff9,0xbf46e22a,0x3f1b02c6,0xbf4bbbf8,0x3f14b039,0xbf5064af,
0x3f226799,0xbf45e403,0x3f1b02c6,0xbf4bbbf8,0x3f13682a,0xbf514d3d,0x3f0b9a6b,0xbf5695e5,0x3f039c3d,0xbf5b941a,0x3ef6e0cb,0xbf604621,0x3ee63375,0xbf64aa59,0x3ed53641,0xbf68bf3c,
0x3f039c3d,0xbf5b941a,0x3ef41f07,0xbf6106f2,0x3ee0924f,0xbf660f88,0x3ecc9b8b,0xbf6aab7b,0x3eb8442a,0xbf6ed89e,0x3ea395c5,0xbf7294f8,0x3e8e9a22,0xbf75dec6,0x3e72b651,0xbf78b47b,
0x3ec3ef15,0xbf6c835e,0x3eac7cd4,0xbf710908,0x3e94a031,0xbf74fa0b,0x3e78cfcc,0xbf7853f8,0x3e47c5c2,0xbf7b14be,0x3e164083,0xbf7d3aac,0x3dc8bd36,0xbf7ec46d,0x3d48fb30,0xbf7fb10f,
0x3e78cfcc,0xbf7853f8,0x3e419b37,0xbf7b61fc,0x3e09cf86,0xbf7dabcc,0x3da3308c,0xbf7f2f9d,0x3cc90ab0,0xbf7fec43,0xbcfb49ba,0xbf7fe129,0xbdafb680,0xbf7f0e58,0xbe1008b7,0xbf7d7474,
0x3dc8bd36,0xbf7ec46d,0x3d16c32c,0xbf7fd397,0xbcc90ab0,0xbf7fec43,0xbdafb680,0xbf7f0e58,0xbe164083,0xbf7d3aac,0xbe541501,0xbf7a7302,0xbe888e93,0xbf76ba07,0xbea68f12,0xbf721352,
0xbd48fb30,0xbf7fb10f,0xbdee3876,0xbf7e4323,0xbe3b6ecf,0xbf7baccd,0xbe7ee6e1,0xbf77f110,0xbea09ae5,0xbf731447,0xbec1071e,0xbf6d1c1d,0xbee0924f,0xbf660f88,0xbeff17b2,0xbf5df6be,
0xbe47c5c2,0xbf7b14be,0xbe888e93,0xbf76ba07,0xbeac7cd4,0xbf710908,0xbecf7bca,0xbf6a09a7,0xbef15aea,0xbf61c598,0xbf08f59b,0xbf584853,0xbf187fc0,0xbf4d9f02,0xbf273656,0xbf41d870,
0xbeac7cd4,0xbf710908,0xbed25a09,0xbf696591,0xbef6e0cb,0xbf604621,0xbf0cead0,0xbf55b993,0xbf1d7fd1,0xbf49d112,0xbf2d1469,0xbf3ca003,0xbf3b8f3b,0xbf2e3bde,0xbf48d8b3,0xbf1ebc12,
0xbef15aea,0xbf61c598,0xbf0b9a6b,0xbf5695e5,0xbf1d7fd1,0xbf49d112,0xbf2e3bde,0xbf3b8f3b,0xbf3daef9,0xbf2beb4a,0xbf4bbbf8,0xbf1b02c6,0xbf584853,0xbf08f59b,0xbf633c5a,0xbeebcbbb,
0xbf187fc0,0xbf4d9f02,0xbf2ac082,0xbf3ebc1b,0xbf3b8f3b,0xbf2e3bde,0xbf4ac77f,0xbf1c420c,0xbf584853,0xbf08f59b,0xbf63f473,0xbee900b7,0xbf6db293,0xbebe1d4a,0xbf756d97,0xbe919ddd,
0xbf3504f3,0xbf3504f3,0xbf45e403,0xbf226799,0xbf54db31,0xbf0e39da,0xbf61c598,0xbef15aea,0xbf6c835e,0xbec3ef15,0xbf74fa0b,0xbe94a031,0xbf7b14be,0xbe47c5c2,0xbf7ec46d,0xbdc8bd36,
0xbf4d9f02,0xbf187fc0,0xbf5c61c7,0xbf0242b1,0xbf68bf3c,0xbed53641,0xbf7294f8,0xbea395c5,0xbf79c79d,0xbe605c13,0xbf7e4323,0xbdee3876,0xbf7ffb11,0xbc490e90,0xbf7eea9d,0x3dbc3ac3,
0xbf61c598,0xbef15aea,0xbf6db293,0xbebe1d4a,0xbf76ba07,0xbe888e93,0xbf7cbfc9,0xbe22abb6,0xbf7fb10f,0xbd48fb30,0xbf7f84ab,0x3d7b2b74,0xbf7c3b28,0x3e2f10a2,0xbf75dec6,0x3e8e9a22,
0xbf710908,0xbeac7cd4,0xbf796e4e,0xbe667c66,0xbf7e70b0,0xbde1bc2e,0xbf7ffec4,0x3bc90f88,0xbf7e1324,0x3dfab273,0xbf78b47b,0x3e72b651,0xbf6ff573,0x3eb263ef,0xbf63f473,0x3ee900b7,
0xbf7b14be,0xbe47c5c2,0xbf7f4e6d,0xbd96a905,0xbf7fb10f,0x3d48fb30,0xbf7c3b28,0x3e2f10a2,0xbf74fa0b,0x3e94a031,0xbf6a09a7,0x3ecf7bca,0xbf5b941a,0x3f039c3d,0xbf49d112,0x3f1d7fd1,
0xbf7fb10f,0xbd48fb30,0xbf7f2f9d,0x3da3308c,0xbf7a7302,0x3e541501,0xbf718f57,0x3ea986c4,0xbf64aa59,0x3ee63375,0xbf53fac3,0x3f0f8784,0xbf3fc767,0x3f299415,0xbf286605,0x3f40d0da,
0xbf7ec46d,0x3dc8bd36,0xbf791298,0x3e6c9a7f,0xbf6ed89e,0x3eb8442a,0xbf604621,0x3ef6e0cb,0xbf4d9f02,0x3f187fc0,0xbf373a23,0x3f32c8c9,0xbf1d7fd1,0x3f49d112,0xbf00e7e4,0x3f5d2d53,
0xbf7853f8,0x3e78cfcc,0xbf6d1c1d,0x3ec1071e,0xbf5d2d53,0x3f00e7e4,0xbf48d8b3,0x3f1ebc12,0xbf3085bb,0x3f396842,0xbf14b039,0x3f5064af,0xbeebcbbb,0x3f633c5a,0xbea986c4,0x3f718f57,
0xbf6c835e,0x3ec3ef15,0xbf5b941a,0x3f039c3d,0xbf45e403,0x3f226799,0xbf2beb4a,0x3f3daef9,0xbf0e39da,0x3f54db31,0xbedae880,0x3f676bd8,0xbe94a031,0x3f74fa0b,0xbe164083,0x3f7d3aac,
0xbf5b941a,0x3f039c3d,0xbf44e3f5,0x3f239da9,0xbf299415,0x3f3fc767,0xbf0a48ad,0x3f577026,0xbecf7bca,0x3f6a09a7,0xbe8586ce,0x3f772417,0xbde1bc2e,0x3f7e70b0,0x3d2fe007,0x3f7fc38f,
0xbf45e403,0x3f226799,0xbf299415,0x3f3fc767,0xbf08f59b,0x3f584853,0xbec9b953,0x3f6b4b0c,0xbe78cfcc,0x3f7853f8,0xbdafb680,0x3f7f0e58,0x3d96a905,0x3f7f4e6d,0x3e6c9a7f,0x3f791298,
0xbf2beb4a,0x3f3daef9,0xbf0a48ad,0x3f577026,0xbec9b953,0x3f6b4b0c,0xbe72b651,0x3f78b47b,0xbd96a905,0x3f7f4e6d,0x3dbc3ac3,0x3f7eea9d,0x3e827dc0,0x3f778bc5,0x3ed25a09,0x3f696591,
0xbf0e39da,0x3f54db31,0xbecf7bca,0x3f6a09a7,0xbe78cfcc,0x3f7853f8,0xbd96a905,0x3f7f4e6d,0x3dc8bd36,0x3f7ec46d,0x3e888e93,0x3f76ba07,0x3edae880,0x3f676bd8,0x3f13682a,0x3f514d3d,
0xbedae880,0x3f676bd8,0xbe8586ce,0x3f772417,0xbdafb680,0x3f7f0e58,0x3dbc3ac3,0x3f7eea9d,0x3e888e93,0x3f76ba07,0x3eddbe79,0x3f66becc,0x3f15f6d9,0x3f4f7a1f,0x3f385216,0x3f31a81d,
0xbe94a031,0x3f74fa0b,0xbde1bc2e,0x3f7e70b0,0x3d96a905,0x3f7f4e6d,0x3e827dc0,0x3f778bc5,0x3edae880,0x3f676bd8,0x3f15f6d9,0x3f4f7a1f,0x3f396842,0x3f3085bb,0x3f5695e5,0x3f0b9a6b,
0xbe164083,0x3f7d3aac,0x3d2fe007,0x3f7fc38f,0x3e6c9a7f,0x3f791298,0x3ed25a09,0x3f696591,0x3f13682a,0x3f514d3d,0x3f385216,0x3f31a81d,0x3f5695e5,0x3f0b9a6b,0x3f6d1c1d,0x3ec1071e,
0xbd803d80,0x80003e00,0x80003e00,0x80003e00,0x80003e00,0x80003e00,0x80003e00,0x80003e00,0x80003e00,0x80003e00,0x80003e00,0x80003e00,0x80003e00,0x80003e00,0x80003e00,0x80003e00,
0x3d803d80,0x3cc83dfb,0x3e000000,0x3dfbbcc8,0x3d443ded,0x3d8e3dd5,0x3dedbd44,0x3dd5bd8e,0x3db53db5,0x3dd53d8e,0x3db5bdb5,0x3d8ebdd5,0x3ded3d44,0x3dfb3cc8,0x3d44bded,0x3cc8bdfb,
0xbd803d80,0x3d443ded,0x8000be00,0xbd44bded,0x3db53db5,0x3ded3d44,0xbdb5bdb5,0xbdedbd44,0x3e000000,0x3dedbd44,0xbe000000,0xbded3d44,0x3db5bdb5,0x3d44bded,0xbdb53db5,0xbd443ded,
0x3d803d80,0x3d8e3dd5,0xbe000000,0xbdd53d8e,0x3ded3d44,0x3dfbbcc8,0xbd443ded,0x3cc83dfb,0x3db5bdb5,0x3cc8bdfb,0x3db53db5,0x3dfb3cc8,0xbd44bded,0xbdd5bd8e,0x3dedbd44,0x3d8ebdd5,
0xbd803d80,0x3db53db5,0x80003e00,0x3db53db5,0x3e000000,0x3db5bdb5,0x3e000000,0x3db5bdb5,0x8000be00,0xbdb5bdb5,0x8000be00,0xbdb5bdb5,0xbe000000,0xbdb53db5,0xbe000000,0xbdb53db5,
0x3d803d80,0x3dd53d8e,0x3e000000,0x3d8ebdd5,0x3dedbd44,0x3cc8bdfb,0xbd44bded,0xbdfbbcc8,0xbdb5bdb5,0xbdfb3cc8,0xbdb53db5,0x3cc83dfb,0xbd443ded,0x3d8e3dd5,0x3ded3d44,0x3dd5bd8e,
0xbd803d80,0x3ded3d44,0x8000be00,0xbdedbd44,0x3db5bdb5,0xbd44bded,0xbdb53db5,0x3d443ded,0xbe000000,0xbd443ded,0x3e000000,0x3d44bded,0x3db53db5,0x3dedbd44,0xbdb5bdb5,0xbded3d44,
0x3d803d80,0x3dfb3cc8,0xbe000000,0xbcc83dfb,0x3d44bded,0xbdd5bd8e,0x3ded3d44,0x3d8ebdd5,0xbdb53db5,0x3d8e3dd5,0xbdb5bdb5,0xbdd53d8e,0x3dedbd44,0xbcc8bdfb,0x3d443ded,0x3dfbbcc8,
0xbd803d80,0x3e000000,0x80003e00,0x3e000000,0x8000be00,0xbe000000,0x8000be00,0xbe000000,0x80003e00,0x3e000000,0x80003e00,0x3e000000,0x8000be00,0xbe000000,0x8000be00,0xbe000000,
0x3d803d80,0x3dfbbcc8,0x3e000000,0xbcc8bdfb,0xbd44bded,0xbdd53d8e,0xbded3d44,0x3d8e3dd5,0x3db53db5,0x3d8ebdd5,0x3db5bdb5,0xbdd5bd8e,0xbdedbd44,0xbcc83dfb,0xbd443ded,0x3dfb3cc8,
0xbd803d80,0x3dedbd44,0x8000be00,0xbded3d44,0xbdb5bdb5,0xbd443ded,0x3db53db5,0x3d44bded,0x3e000000,0xbd44bded,0xbe000000,0x3d443ded,0xbdb53db5,0x3ded3d44,0x3db5bdb5,0xbdedbd44,
0x3d803d80,0x3dd5bd8e,0xbe000000,0x3d8e3dd5,0xbdedbd44,0x3cc83dfb,0x3d44bded,0xbdfb3cc8,0x3db5bdb5,0xbdfbbcc8,0x3db53db5,0x3cc8bdfb,0x3d443ded,0x3d8ebdd5,0xbded3d44,0x3dd53d8e,
0xbd803d80,0x3db5bdb5,0x80003e00,0x3db5bdb5,0xbe000000,0x3db53db5,0xbe000000,0x3db53db5,0x8000be00,0xbdb53db5,0x8000be00,0xbdb53db5,0x3e000000,0xbdb5bdb5,0x3e000000,0xbdb5bdb5,
0x3d803d80,0x3d8ebdd5,0x3e000000,0xbdd5bd8e,0xbded3d44,0x3dfb3cc8,0x3d443ded,0x3cc8bdfb,0xbdb5bdb5,0x3cc83dfb,0xbdb53db5,0x3dfbbcc8,0x3d44bded,0xbdd53d8e,0xbdedbd44,0x3d8e3dd5,
0xbd803d80,0x3d44bded,0x8000be00,0xbd443ded,0xbdb53db5,0x3dedbd44,0x3db5bdb5,0xbded3d44,0xbe000000,0x3ded3d44,0x3e000000,0xbdedbd44,0xbdb5bdb5,0x3d443ded,0x3db53db5,0xbd44bded,
0x3d803d80,0x3cc8bdfb,0xbe000000,0x3dfb3cc8,0xbd443ded,0x3d8ebdd5,0xbdedbd44,0x3dd53d8e,0xbdb53db5,0x3dd5bd8e,0xbdb5bdb5,0x3d8e3dd5,0xbded3d44,0x3dfbbcc8,0xbd44bded,0x3cc83dfb,
0xbd803d80,0x8000be00,0x80003e00,0x8000be00,0x80003e00,0x8000be00,0x80003e00,0x8000be00,0x80003e00,0x8000be00,0x80003e00,0x8000be00,0x80003e00,0x8000be00,0x80003e00,0x8000be00,
0x3d803d80,0xbcc8bdfb,0x3e000000,0xbdfb3cc8,0x3d443ded,0xbd8ebdd5,0x3dedbd44,0xbdd53d8e,0x3db53db5,0xbdd5bd8e,0x3db5bdb5,0xbd8e3dd5,0x3ded3d44,0xbdfbbcc8,0x3d44bded,0xbcc83dfb,
0xbd803d80,0xbd44bded,0x8000be00,0x3d443ded,0x3db53db5,0xbdedbd44,0xbdb5bdb5,0x3ded3d44,0x3e000000,0xbded3d44,0xbe000000,0x3dedbd44,0x3db5bdb5,0xbd443ded,0xbdb53db5,0x3d44bded,
0x3d803d80,0xbd8ebdd5,0xbe000000,0x3dd5bd8e,0x3ded3d44,0xbdfb3cc8,0xbd443ded,0xbcc8bdfb,0x3db5bdb5,0xbcc83dfb,0x3db53db5,0xbdfbbcc8,0xbd44bded,0x3dd53d8e,0x3dedbd44,0xbd8e3dd5,
0xbd803d80,0xbdb5bdb5,0x80003e00,0xbdb5bdb5,0x3e000000,0xbdb53db5,0x3e000000,0xbdb53db5,0x8000be00,0x3db53db5,0x8000be00,0x3db53db5,0xbe000000,0x3db5bdb5,0xbe000000,0x3db5bdb5,
0x3d803d80,0xbdd5bd8e,0x3e000000,0xbd8e3dd5,0x3dedbd44,0xbcc83dfb,0xbd44bded,0x3dfb3cc8,0xbdb5bdb5,0x3dfbbcc8,0xbdb53db5,0xbcc8bdfb,0xbd443ded,0xbd8ebdd5,0x3ded3d44,0xbdd53d8e,
0xbd803d80,0xbdedbd44,0x8000be00,0x3ded3d44,0x3db5bdb5,0x3d443ded,0xbdb53db5,0xbd44bded,0xbe000000,0x3d44bded,0x3e000000,0xbd443ded,0x3db53db5,0xbded3d44,0xbdb5bdb5,0x3dedbd44,
0x3d803d80,0xbdfbbcc8,0xbe000000,0x3cc8bdfb,0x3d44bded,0x3dd53d8e,0x3ded3d44,0xbd8e3dd5,0xbdb53db5,0xbd8ebdd5,0xbdb5bdb5,0x3dd5bd8e,0x3dedbd44,0x3cc83dfb,0x3d443ded,0xbdfb3cc8,
0xbd803d80,0xbe000000,0x80003e00,0xbe000000,0x8000be00,0x3e000000,0x8000be00,0x3e000000,0x80003e00,0xbe000000,0x80003e00,0xbe000000,0x8000be00,0x3e000000,0x8000be00,0x3e000000,
0x3d803d80,0xbdfb3cc8,0x3e000000,0x3cc83dfb,0xbd44bded,0x3dd5bd8e,0xbded3d44,0xbd8ebdd5,0x3db53db5,0xbd8e3dd5,0x3db5bdb5,0x3dd53d8e,0xbdedbd44,0x3cc8bdfb,0xbd443ded,0xbdfbbcc8,
0xbd803d80,0xbded3d44,0x8000be00,0x3dedbd44,0xbdb5bdb5,0x3d44bded,0x3db53db5,0xbd443ded,0x3e000000,0x3d443ded,0xbe000000,0xbd44bded,0xbdb53db5,0xbdedbd44,0x3db5bdb5,0x3ded3d44,
0x3d803d80,0xbdd53d8e,0xbe000000,0xbd8ebdd5,0xbdedbd44,0xbcc8bdfb,0x3d44bded,0x3dfbbcc8,0x3db5bdb5,0x3dfb3cc8,0x3db53db5,0xbcc83dfb,0x3d443ded,0xbd8e3dd5,0xbded3d44,0xbdd5bd8e,
0xbd803d80,0xbdb53db5,0x80003e00,0xbdb53db5,0xbe000000,0xbdb5bdb5,0xbe000000,0xbdb5bdb5,0x8000be00,0x3db5bdb5,0x8000be00,0x3db5bdb5,0x3e000000,0x3db53db5,0x3e000000,0x3db53db5,
0x3d803d80,0xbd8e3dd5,0x3e000000,0x3dd53d8e,0xbded3d44,0xbdfbbcc8,0x3d443ded,0xbcc83dfb,0xbdb5bdb5,0xbcc8bdfb,0xbdb53db5,0xbdfb3cc8,0x3d44bded,0x3dd5bd8e,0xbdedbd44,0xbd8ebdd5,
0xbd803d80,0xbd443ded,0x8000be00,0x3d44bded,0xbdb53db5,0xbded3d44,0x3db5bdb5,0x3dedbd44,0xbe000000,0xbdedbd44,0x3e000000,0x3ded3d44,0xbdb5bdb5,0xbd44bded,0x3db53db5,0x3d443ded,
0x3d803d80,0xbcc83dfb,0xbe000000,0xbdfbbcc8,0xbd443ded,0xbd8e3dd5,0xbdedbd44,0xbdd5bd8e,0xbdb53db5,0xbdd53d8e,0xbdb5bdb5,0xbd8ebdd5,0xbded3d44,0xbdfb3cc8,0xbd44bded,0xbcc8bdfb,
0x80003e00,0x80003e00,0x80003e00,0x80003e00,0x80003e00,0x80003e00,0x80003e00,0x80003e00,0x80003e00,0x80003e00,0x80003e00,0x80003e00,0x80003e00,0x80003e00,0x80003e00,0x80003e00,
0x3c493dff,0x3d153df5,0x3dffbc49,0x3df5bd15,0x3d713de2,0x3da23dc6,0x3de2bd71,0x3dc6bda2,0x3dc63da2,0x3de23d71,0x3da2bdc6,0x3d71bde2,0x3df53d15,0x3dff3c49,0x3d15bdf5,0x3c49bdff,
0x3cc83dfb,0x3d8e3dd5,0xbcc8bdfb,0xbd8ebdd5,0x3dd53d8e,0x3dfb3cc8,0xbdd5bd8e,0xbdfbbcc8,0x3dfbbcc8,0x3dd5bd8e,0xbdfb3cc8,0xbdd53d8e,0x3d8ebdd5,0x3cc8bdfb,0xbd8e3dd5,0xbcc83dfb,
0x3d153df5,0x3dc63da2,0xbdf53d15,0xbda23dc6,0x3dff3c49,0x3de2bd71,0xbc493dff,0x3d713de2,0x3d71bde2,0xbc49bdff,0x3de23d71,0x3dffbc49,0xbda2bdc6,0xbdf5bd15,0x3dc6bda2,0x3d15bdf5,
0x3d443ded,0x3ded3d44,0x3d443ded,0x3ded3d44,0x3dedbd44,0x3d44bded,0x3dedbd44,0x3d44bded,0xbd44bded,0xbdedbd44,0xbd44bded,0xbdedbd44,0xbded3d44,0xbd443ded,0xbded3d44,0xbd443ded,
0x3d713de2,0x3dff3c49,0x3de2bd71,0x3c49bdff,0x3da2bdc6,0xbd15bdf5,0xbdc6bda2,0xbdf53d15,0xbdf5bd15,0xbdc63da2,0xbd153df5,0x3da23dc6,0x3c493dff,0x3de23d71,0x3dffbc49,0x3d71bde2,
0x3d8e3dd5,0x3dfbbcc8,0xbd8ebdd5,0xbdfb3cc8,0x3cc8bdfb,0xbdd5bd8e,0xbcc83dfb,0x3dd53d8e,0xbdd53d8e,0x3cc83dfb,0x3dd5bd8e,0xbcc8bdfb,0x3dfb3cc8,0x3d8ebdd5,0xbdfbbcc8,0xbd8e3dd5,
0x3da23dc6,0x3de2bd71,0xbdc63da2,0x3d713de2,0xbd15bdf5,0xbdff3c49,0x3df5bd15,0xbc49bdff,0xbc493dff,0x3df53d15,0xbdffbc49,0xbd153df5,0x3d71bde2,0xbdc6bda2,0x3de23d71,0x3da2bdc6,
0x3db53db5,0x3db5bdb5,0x3db53db5,0x3db5bdb5,0xbdb5bdb5,0xbdb53db5,0xbdb5bdb5,0xbdb53db5,0x3db53db5,0x3db5bdb5,0x3db53db5,0x3db5bdb5,0xbdb5bdb5,0xbdb53db5,0xbdb5bdb5,0xbdb53db5,
0x3dc63da2,0x3d71bde2,0x3da2bdc6,0xbde2bd71,0xbdf5bd15,0xbc493dff,0xbd153df5,0x3dff3c49,0x3dffbc49,0xbd15bdf5,0xbc49bdff,0xbdf53d15,0xbde23d71,0x3da23dc6,0x3d713de2,0x3dc6bda2,
0x3dd53d8e,0x3cc8bdfb,0xbdd5bd8e,0xbcc83dfb,0xbdfb3cc8,0x3d8e3dd5,0x3dfbbcc8,0xbd8ebdd5,0x3d8ebdd5,0xbdfbbcc8,0xbd8e3dd5,0x3dfb3cc8,0x3cc83dfb,0x3dd5bd8e,0xbcc8bdfb,0xbdd53d8e,
0x3de23d71,0xbc49bdff,0xbd713de2,0x3dffbc49,0xbdc63da2,0x3df53d15,0xbda2bdc6,0xbd153df5,0xbd15bdf5,0xbda23dc6,0x3df5bd15,0xbdc6bda2,0x3dff3c49,0xbd71bde2,0xbc493dff,0x3de2bd71,
0x3ded3d44,0xbd44bded,0x3ded3d44,0xbd44bded,0xbd443ded,0x3dedbd44,0xbd443ded,0x3dedbd44,0xbdedbd44,0x3d443ded,0xbdedbd44,0x3d443ded,0x3d44bded,0xbded3d44,0x3d44bded,0xbded3d44,
0x3df53d15,0xbda2bdc6,0x3d15bdf5,0xbdc63da2,0x3c493dff,0x3d71bde2,0x3dffbc49,0xbde2bd71,0xbde23d71,0x3dff3c49,0x3d713de2,0x3c49bdff,0xbdc6bda2,0x3d153df5,0xbda23dc6,0x3df5bd15,
0x3dfb3cc8,0xbdd5bd8e,0xbdfbbcc8,0x3dd53d8e,0x3d8e3dd5,0xbcc8bdfb,0xbd8ebdd5,0x3cc83dfb,0xbcc83dfb,0x3d8ebdd5,0x3cc8bdfb,0xbd8e3dd5,0xbdd53d8e,0x3dfbbcc8,0x3dd5bd8e,0xbdfb3cc8,
0x3dff3c49,0xbdf5bd15,0xbc493dff,0x3d15bdf5,0x3de23d71,0xbdc6bda2,0xbd713de2,0x3da2bdc6,0x3da23dc6,0xbd71bde2,0xbdc63da2,0x3de2bd71,0x3d153df5,0xbc49bdff,0xbdf53d15,0x3dffbc49,
0x3e000000,0xbe000000,0x3e000000,0xbe000000,0x3e000000,0xbe000000,0x3e000000,0xbe000000,0x3e000000,0xbe000000,0x3e000000,0xbe000000,0x3e000000,0xbe000000,0x3e000000,0xbe000000,
0x3dffbc49,0xbdf53d15,0xbc49bdff,0x3d153df5,0x3de2bd71,0xbdc63da2,0xbd71bde2,0x3da23dc6,0x3da2bdc6,0xbd713de2,0xbdc6bda2,0x3de23d71,0x3d15bdf5,0xbc493dff,0xbdf5bd15,0x3dff3c49,
0x3dfbbcc8,0xbdd53d8e,0xbdfb3cc8,0x3dd5bd8e,0x3d8ebdd5,0xbcc83dfb,0xbd8e3dd5,0x3cc8bdfb,0xbcc8bdfb,0x3d8e3dd5,0x3cc83dfb,0xbd8ebdd5,0xbdd5bd8e,0x3dfb3cc8,0x3dd53d8e,0xbdfbbcc8,
0x3df5bd15,0xbda23dc6,0x3d153df5,0xbdc6bda2,0x3c49bdff,0x3d713de2,0x3dff3c49,0xbde23d71,0xbde2bd71,0x3dffbc49,0x3d71bde2,0x3c493dff,0xbdc63da2,0x3d15bdf5,0xbda2bdc6,0x3df53d15,
0x3dedbd44,0xbd443ded,0x3dedbd44,0xbd443ded,0xbd44bded,0x3ded3d44,0xbd44bded,0x3ded3d44,0xbded3d44,0x3d44bded,0xbded3d44,0x3d44bded,0x3d443ded,0xbdedbd44,0x3d443ded,0xbdedbd44,
0x3de2bd71,0xbc493dff,0xbd71bde2,0x3dff3c49,0xbdc6bda2,0x3df5bd15,0xbda23dc6,0xbd15bdf5,0xbd153df5,0xbda2bdc6,0x3df53d15,0xbdc63da2,0x3dffbc49,0xbd713de2,0xbc49bdff,0x3de23d71,
0x3dd5bd8e,0x3cc83dfb,0xbdd53d8e,0xbcc8bdfb,0xbdfbbcc8,0x3d8ebdd5,0x3dfb3cc8,0xbd8e3dd5,0x3d8e3dd5,0xbdfb3cc8,0xbd8ebdd5,0x3dfbbcc8,0x3cc8bdfb,0x3dd53d8e,0xbcc83dfb,0xbdd5bd8e,
0x3dc6bda2,0x3d713de2,0x3da23dc6,0xbde23d71,0xbdf53d15,0xbc49bdff,0xbd15bdf5,0x3dffbc49,0x3dff3c49,0xbd153df5,0xbc493dff,0xbdf5bd15,0xbde2bd71,0x3da2bdc6,0x3d71bde2,0x3dc63da2,
0x3db5bdb5,0x3db53db5,0x3db5bdb5,0x3db53db5,0xbdb53db5,0xbdb5bdb5,0xbdb53db5,0xbdb5bdb5,0x3db5bdb5,0x3db53db5,0x3db5bdb5,0x3db53db5,0xbdb53db5,0xbdb5bdb5,0xbdb53db5,0xbdb5bdb5,
0x3da2bdc6,0x3de23d71,0xbdc6bda2,0x3d71bde2,0xbd153df5,0xbdffbc49,0x3df53d15,0xbc493dff,0xbc49bdff,0x3df5bd15,0xbdff3c49,0xbd15bdf5,0x3d713de2,0xbdc63da2,0x3de2bd71,0x3da23dc6,
0x3d8ebdd5,0x3dfb3cc8,0xbd8e3dd5,0xbdfbbcc8,0x3cc83dfb,0xbdd53d8e,0xbcc8bdfb,0x3dd5bd8e,0xbdd5bd8e,0x3cc8bdfb,0x3dd53d8e,0xbcc83dfb,0x3dfbbcc8,0x3d8e3dd5,0xbdfb3cc8,0xbd8ebdd5,
0x3d71bde2,0x3dffbc49,0x3de23d71,0x3c493dff,0x3da23dc6,0xbd153df5,0xbdc63da2,0xbdf5bd15,0xbdf53d15,0xbdc6bda2,0xbd15bdf5,0x3da2bdc6,0x3c49bdff,0x3de2bd71,0x3dff3c49,0x3d713de2,
0x3d44bded,0x3dedbd44,0x3d44bded,0x3dedbd44,0x3ded3d44,0x3d443ded,0x3ded3d44,0x3d443ded,0xbd443ded,0xbded3d44,0xbd443ded,0xbded3d44,0xbdedbd44,0xbd44bded,0xbdedbd44,0xbd44bded,
0x3d15bdf5,0x3dc6bda2,0xbdf5bd15,0xbda2bdc6,0x3dffbc49,0x3de23d71,0xbc49bdff,0x3d71bde2,0x3d713de2,0xbc493dff,0x3de2bd71,0x3dff3c49,0xbda23dc6,0xbdf53d15,0x3dc63da2,0x3d153df5,
0x3cc8bdfb,0x3d8ebdd5,0xbcc83dfb,0xbd8e3dd5,0x3dd5bd8e,0x3dfbbcc8,0xbdd53d8e,0xbdfb3cc8,0x3dfb3cc8,0x3dd53d8e,0xbdfbbcc8,0xbdd5bd8e,0x3d8e3dd5,0x3cc83dfb,0xbd8ebdd5,0xbcc8bdfb,
0x3c49bdff,0x3d15bdf5,0x3dff3c49,0x3df53d15,0x3d71bde2,0x3da2bdc6,0x3de23d71,0x3dc63da2,0x3dc6bda2,0x3de2bd71,0x3da23dc6,0x3d713de2,0x3df5bd15,0x3dffbc49,0x3d153df5,0x3c493dff,
0x3f800000,0x0,0x3f800000,0x0,0x3f800000,0x0,0x3f800000,0x0,0x3f800000,0x0,0x3f800000,0x0,0x3f800000,0x0,0x3f800000,0x0,
0x3f800000,0x0,0x3f7ffb11,0xbc490e90,0x3f7fec43,0xbcc90ab0,0x3f7fd397,0xbd16c32c,0x3f7fb10f,0xbd48fb30,0x3f7f84ab,0xbd7b2b74,0x3f7f4e6d,0xbd96a905,0x3f7f0e58,0xbdafb680,
0x3f800000,0x0,0x3f7fec43,0xbcc90ab0,0x3f7fb10f,0xbd48fb30,0x3f7f4e6d,0xbd96a905,0x3f7ec46d,0xbdc8bd36,0x3f7e1324,0xbdfab273,0x3f7d3aac,0xbe164083,0x3f7c3b28,0xbe2f10a2,
0x3f800000,0x0,0x3f7fd397,0xbd16c32c,0x3f7f4e6d,0xbd96a905,0x3f7e70b0,0xbde1bc2e,0x3f7d3aac,0xbe164083,0x3f7baccd,0xbe3b6ecf,0x3f79c79d,0xbe605c13,0x3f778bc5,0xbe827dc0,
0x3f800000,0x0,0x3f7fb10f,0xbd48fb30,0x3f7ec46d,0xbdc8bd36,0x3f7d3aac,0xbe164083,0x3f7b14be,0xbe47c5c2,0x3f7853f8,0xbe78cfcc,0x3f74fa0b,0xbe94a031,0x3f710908,0xbeac7cd4,
0x3f800000,0x0,0x3f7f84ab,0xbd7b2b74,0x3f7e1324,0xbdfab273,0x3f7baccd,0xbe3b6ecf,0x3f7853f8,0xbe78cfcc,0x3f740bdd,0xbe9aa086,0x3f6ed89e,0xbeb8442a,0x3f68bf3c,0xbed53641,
0x3f800000,0x0,0x3f7f4e6d,0xbd96a905,0x3f7d3aac,0xbe164083,0x3f79c79d,0xbe605c13,0x3f74fa0b,0xbe94a031,0x3f6ed89e,0xbeb8442a,0x3f676bd8,0xbedae880,0x3f5ebe05,0xbefc5d27,
0x3f800000,0x0,0x3f7f0e58,0xbdafb680,0x3f7c3b28,0xbe2f10a2,0x3f778bc5,0xbe827dc0,0x3f710908,0xbeac7cd4,0x3f68bf3c,0xbed53641,0x3f5ebe05,0xbefc5d27,0x3f531849,0xbf10d3cd,
0x3f800000,0x0,0x3f7ec46d,0xbdc8bd36,0x3f7b14be,0xbe47c5c2,0x3f74fa0b,0xbe94a031,0x3f6c835e,0xbec3ef15,0x3f61c598,0xbef15aea,0x3f54db31,0xbf0e39da,0x3f45e403,0xbf226799,
0x3f800000,0x0,0x3f7e70b0,0xbde1bc2e,0x3f79c79d,0xbe605c13,0x3f721352,0xbea68f12,0x3f676bd8,0xbedae880,0x3f59f26a,0xbf064b82,0x3f49d112,0xbf1d7fd1,0x3f373a23,0xbf32c8c9,
0x3f800000,0x0,0x3f7e1324,0xbdfab273,0x3f7853f8,0xbe78cfcc,0x3f6ed89e,0xbeb8442a,0x3f61c598,0xbef15aea,0x3f514d3d,0xbf13682a,0x3f3daef9,0xbf2beb4a,0x3f273656,0xbf41d870,
0x3f800000,0x0,0x3f7dabcc,0xbe09cf86,0x3f76ba07,0xbe888e93,0x3f6b4b0c,0xbec9b953,0x3f5b941a,0xbf039c3d,0x3f47de65,0xbf1ff6cb,0x3f3085bb,0xbf396842,0x3f15f6d9,0xbf4f7a1f,
0x3f800000,0x0,0x3f7d3aac,0xbe164083,0x3f74fa0b,0xbe94a031,0x3f676bd8,0xbedae880,0x3f54db31,0xbf0e39da,0x3f3daef9,0xbf2beb4a,0x3f226799,0xbf45e403,0x3f039c3d,0xbf5b941a,
0x3f800000,0x0,0x3f7cbfc9,0xbe22abb6,0x3f731447,0xbea09ae5,0x3f633c5a,0xbeebcbbb,0x3f4d9f02,0xbf187fc0,0x3f32c8c9,0xbf373a23,0x3f13682a,0xbf514d3d,0x3ee0924f,0xbf660f88,
0x3f800000,0x0,0x3f7c3b28,0xbe2f10a2,0x3f710908,0xbeac7cd4,0x3f5ebe05,0xbefc5d27,0x3f45e403,0xbf226799,0x3f273656,0xbf41d870,0x3f039c3d,0xbf5b941a,0x3eb8442a,0xbf6ed89e,
0x3f800000,0x0,0x3f7baccd,0xbe3b6ecf,0x3f6ed89e,0xbeb8442a,0x3f59f26a,0xbf064b82,0x3f3daef9,0xbf2beb4a,0x3f1b02c6,0xbf4bbbf8,0x3ee63375,0xbf64aa59,0x3e8e9a22,0xbf75dec6,
0x3f800000,0x0,0x3f7b14be,0xbe47c5c2,0x3f6c835e,0xbec3ef15,0x3f54db31,0xbf0e39da,0x3f3504f3,0xbf3504f3,0x3f0e39da,0xbf54db31,0x3ec3ef15,0xbf6c835e,0x3e47c5c2,0xbf7b14be,
0x3f800000,0x0,0x3f7a7302,0xbe541501,0x3f6a09a7,0xbecf7bca,0x3f4f7a1f,0xbf15f6d9,0x3f2beb4a,0xbf3daef9,0x3f00e7e4,0xbf5d2d53,0x3ea09ae5,0xbf731447,0x3de1bc2e,0xbf7e70b0,
0x3f800000,0x0,0x3f79c79d,0xbe605c13,0x3f676bd8,0xbedae880,0x3f49d112,0xbf1d7fd1,0x3f226799,0xbf45e403,0x3ee63375,0xbf64aa59,0x3e78cfcc,0xbf7853f8,0x3cc90ab0,0xbf7fec43,
0x3f800000,0x0,0x3f791298,0xbe6c9a7f,0x3f64aa59,0xbee63375,0x3f43e200,0xbf24d225,0x3f187fc0,0xbf4d9f02,0x3ec9b953,0xbf6b4b0c,0x3e2f10a2,0xbf7c3b28,0xbd7b2b74,0xbf7f84ab,
0x3f800000,0x0,0x3f7853f8,0xbe78cfcc,0x3f61c598,0xbef15aea,0x3f3daef9,0xbf2beb4a,0x3f0e39da,0xbf54db31,0x3eac7cd4,0xbf710908,0x3dc8bd36,0xbf7ec46d,0xbe164083,0xbf7d3aac,
0x3f800000,0x0,0x3f778bc5,0xbe827dc0,0x3f5ebe05,0xbefc5d27,0x3f373a23,0xbf32c8c9,0x3f039c3d,0xbf5b941a,0x3e8e9a22,0xbf75dec6,0x3cc90ab0,0xbf7fec43,0xbe6c9a7f,0xbf791298,
0x3f800000,0x0,0x3f76ba07,0xbe888e93,0x3f5b941a,0xbf039c3d,0x3f3085bb,0xbf396842,0x3ef15aea,0xbf61c598,0x3e605c13,0xbf79c79d,0xbd48fb30,0xbf7fb10f,0xbea09ae5,0xbf731447,
0x3f800000,0x0,0x3f75dec6,0xbe8e9a22,0x3f584853,0xbf08f59b,0x3f299415,0xbf3fc767,0x3edae880,0xbf676bd8,0x3e22abb6,0xbf7cbfc9,0xbdfab273,0xbf7e1324,0xbec9b953,0xbf6b4b0c,
0x3f800000,0x0,0x3f74fa0b,0xbe94a031,0x3f54db31,0xbf0e39da,0x3f226799,0xbf45e403,0x3ec3ef15,0xbf6c835e,0x3dc8bd36,0xbf7ec46d,0xbe47c5c2,0xbf7b14be,0xbef15aea,0xbf61c598,
0x3f800000,0x0,0x3f740bdd,0xbe9aa086,0x3f514d3d,0xbf13682a,0x3f1b02c6,0xbf4bbbf8,0x3eac7cd4,0xbf710908,0x3d16c32c,0xbf7fd397,0xbe888e93,0xbf76ba07,0xbf0b9a6b,0xbf5695e5,
0x3f800000,0x0,0x3f731447,0xbea09ae5,0x3f4d9f02,0xbf187fc0,0x3f13682a,0xbf514d3d,0x3e94a031,0xbf74fa0b,0xbcc90ab0,0xbf7fec43,0xbeac7cd4,0xbf710908,0xbf1d7fd1,0xbf49d112,
0x3f800000,0x0,0x3f721352,0xbea68f12,0x3f49d112,0xbf1d7fd1,0x3f0b9a6b,0xbf5695e5,0x3e78cfcc,0xbf7853f8,0xbdafb680,0xbf7f0e58,0xbecf7bca,0xbf6a09a7,0xbf2e3bde,0xbf3b8f3b,
0x3f800000,0x0,0x3f710908,0xbeac7cd4,0x3f45e403,0xbf226799,0x3f039c3d,0xbf5b941a,0x3e47c5c2,0xbf7b14be,0xbe164083,0xbf7d3aac,0xbef15aea,0xbf61c598,0xbf3daef9,0xbf2beb4a,
0x3f800000,0x0,0x3f6ff573,0xbeb263ef,0x3f41d870,0xbf273656,0x3ef6e0cb,0xbf604621,0x3e164083,0xbf7d3aac,0xbe541501,0xbf7a7302,0xbf08f59b,0xbf584853,0xbf4bbbf8,0xbf1b02c6,
0x3f800000,0x0,0x3f6ed89e,0xbeb8442a,0x3f3daef9,0xbf2beb4a,0x3ee63375,0xbf64aa59,0x3dc8bd36,0xbf7ec46d,0xbe888e93,0xbf76ba07,0xbf187fc0,0xbf4d9f02,0xbf584853,0xbf08f59b,
0x3f800000,0x0,0x3f6db293,0xbebe1d4a,0x3f396842,0xbf3085bb,0x3ed53641,0xbf68bf3c,0x3d48fb30,0xbf7fb10f,0xbea68f12,0xbf721352,0xbf273656,0xbf41d870,0xbf633c5a,0xbeebcbbb,
0x3f800000,0x3f800000,0x3f800000,0x3f800000,0x3f800000,0x3f800000,0x3f800000,0x3f800000,0x3f800000,0xbf800000,0x3f800000,0xbf800000,0x3f800000,0xbf800000,0x3f800000,0xbf800000,
0x3f800000,0x3f3504f3,0x0,0xbf3504f3,0xbf800000,0xbf3504f3,0x0,0x3f3504f3,0x0,0xbf3504f3,0xbf800000,0xbf3504f3,0x0,0x3f3504f3,0x3f800000,0x3f3504f3,
0x3f800000,0x0,0xbf800000,0x0,0x3f800000,0x0,0xbf800000,0x0,0x0,0xbf800000,0x0,0x3f800000,0x0,0xbf800000,0x0,0x3f800000,
0x3f800000,0xbf3504f3,0x0,0x3f3504f3,0xbf800000,0x3f3504f3,0x0,0xbf3504f3,0x0,0xbf3504f3,0x3f800000,0xbf3504f3,0x0,0x3f3504f3,0xbf800000,0x3f3504f3,
0x3f800000,0x3f6c835e,0x3f3504f3,0x3ec3ef15,0x0,0xbec3ef15,0xbf3504f3,0xbf6c835e,0x0,0xbec3ef15,0xbf3504f3,0xbf6c835e,0xbf800000,0xbf6c835e,0xbf3504f3,0xbec3ef15,
0x3f800000,0x3ec3ef15,0xbf3504f3,0xbf6c835e,0x0,0x3f6c835e,0x3f3504f3,0xbec3ef15,0x0,0xbf6c835e,0xbf3504f3,0x3ec3ef15,0x3f800000,0x3ec3ef15,0xbf3504f3,0xbf6c835e,
0x3f800000,0xbec3ef15,0xbf3504f3,0x3f6c835e,0x0,0xbf6c835e,0x3f3504f3,0x3ec3ef15,0x0,0xbf6c835e,0x3f3504f3,0x3ec3ef15,0xbf800000,0x3ec3ef15,0x3f3504f3,0xbf6c835e,
0x3f800000,0xbf6c835e,0x3f3504f3,0xbec3ef15,0x0,0x3ec3ef15,0xbf3504f3,0x3f6c835e,0x0,0xbec3ef15,0x3f3504f3,0xbf6c835e,0x3f800000,0xbf6c835e,0x3f3504f3,0xbec3ef15,
};

struct Params {
    const __nv_bfloat16 *wr, *wi, *xb, *lre, *lim, *ldt, *dsk;
    float* out;
};

struct cf { float x, y; };
__device__ __forceinline__ uint32_t smem_u32(const void* p) { return (uint32_t)__cvta_generic_to_shared(p); }
__device__ __forceinline__ void mbar_init(uint32_t a, uint32_t c) { asm volatile("mbarrier.init.shared::cta.b64 [%0], %1;" ::"r"(a), "r"(c) : "memory"); }
__device__ __forceinline__ void mbar_expect_tx(uint32_t a, uint32_t b) { asm volatile("mbarrier.arrive.expect_tx.shared::cta.b64 _, [%0], %1;" ::"r"(a), "r"(b) : "memory"); }
__device__ __forceinline__ void mbar_arrive(uint32_t a) { asm volatile("mbarrier.arrive.shared::cta.b64 _, [%0];" ::"r"(a) : "memory"); }
__device__ __forceinline__ uint32_t mbar_try(uint32_t a, uint32_t ph) {
    uint32_t ok;
    asm volatile("{.reg .pred p; mbarrier.try_wait.parity.shared::cta.b64 p, [%1], %2; selp.u32 %0, 1, 0, p;}" : "=r"(ok) : "r"(a), "r"(ph) : "memory");
    return ok;
}
__device__ __forceinline__ void mbar_wait(uint32_t a, uint32_t ph) {
    uint32_t ok, n = 0;
    do { ok = mbar_try(a, ph); } while (!ok && ++n < SPIN_LIMIT);
}
__device__ __forceinline__ void mbar_wait_fast(uint32_t a, uint32_t ph) { if (!mbar_try(a, ph)) mbar_wait(a, ph); }
__device__ __forceinline__ unsigned ld_rlx(const unsigned* p) { unsigned v; asm volatile("ld.relaxed.gpu.global.u32 %0, [%1];" : "=r"(v) : "l"(p) : "memory"); return v; }
__device__ __forceinline__ void wait_cnt(const unsigned* p, unsigned target) {
    unsigned n = 0;
    while ((int)(ld_rlx(p) - target) < 0 && ++n < SPIN_LIMIT) __nanosleep(20);
}
__device__ __forceinline__ void red_hint(unsigned* p) { asm volatile("red.relaxed.gpu.global.add.u32 [%0], 1;" ::"l"(p) : "memory"); }
__device__ __forceinline__ void fence_async() { asm volatile("fence.proxy.async.global;" ::: "memory"); }
__device__ __forceinline__ void fence_async_sm() { asm volatile("fence.proxy.async.shared::cta;" ::: "memory"); }
#define bar_sync(id, n) asm volatile("bar.sync %0, %1;" ::"n"(id), "n"(n) : "memory")
#define bar_arrive(id, n) asm volatile("bar.arrive %0, %1;" ::"n"(id), "n"(n) : "memory")
__device__ __forceinline__ bool elect_one() {
    uint32_t r;
    asm volatile("{.reg .pred p; elect.sync _|p, 0xffffffff; selp.u32 %0, 1, 0, p;}" : "=r"(r));
    return r != 0;
}

__device__ __forceinline__ void tma2d(uint32_t dst, const CUtensorMap* m, int c0, int c1, uint32_t bar) {
    asm volatile("cp.async.bulk.tensor.2d.shared::cluster.global.mbarrier::complete_tx::bytes [%0], [%1, {%3,%4}], [%2];" ::"r"(dst), "l"(m), "r"(bar), "r"(c0), "r"(c1) : "memory");
}
__device__ __forceinline__ void tma2d_mc(uint32_t dst, const CUtensorMap* m, int c0, int c1, uint32_t bar) {
    asm volatile("cp.async.bulk.tensor.2d.shared::cluster.global.mbarrier::complete_tx::bytes.multicast::cluster [%0], [%1, {%3,%4}], [%2], %5;" ::"r"(dst), "l"(m), "r"(bar), "r"(c0), "r"(c1), "h"((uint16_t)3) : "memory");
}
__device__ __forceinline__ void tma4d(uint32_t dst, const CUtensorMap* m, int c0, int c1, int c2, int c3, uint32_t bar) {
    asm volatile("cp.async.bulk.tensor.4d.shared::cluster.global.mbarrier::complete_tx::bytes [%0], [%1, {%3,%4,%5,%6}], [%2];" ::"r"(dst), "l"(m), "r"(bar), "r"(c0), "r"(c1), "r"(c2), "r"(c3) : "memory");
}
__device__ __forceinline__ void tma2d_st(const CUtensorMap* m, int c0, int c1, uint32_t src) {
    asm volatile("cp.async.bulk.tensor.2d.global.shared::cta.bulk_group [%0, {%2,%3}], [%1];" ::"l"(m), "r"(src), "r"(c0), "r"(c1) : "memory");
}
__device__ __forceinline__ void tma3d_st(const CUtensorMap* m, int c0, int c1, int c2, uint32_t src) {
    asm volatile("cp.async.bulk.tensor.3d.global.shared::cta.bulk_group [%0, {%2,%3,%4}], [%1];" ::"l"(m), "r"(src), "r"(c0), "r"(c1), "r"(c2) : "memory");
}
__device__ __forceinline__ void tma5d(uint32_t dst, const CUtensorMap* m, int c0, int c1, int c2, int c3, int c4, uint32_t bar) {
    asm volatile("cp.async.bulk.tensor.5d.shared::cluster.global.mbarrier::complete_tx::bytes [%0], [%1, {%3,%4,%5,%6,%7}], [%2];" ::"r"(dst), "l"(m), "r"(bar), "r"(c0), "r"(c1), "r"(c2), "r"(c3), "r"(c4) : "memory");
}
__device__ __forceinline__ void bulk_ld(uint32_t dst, const void* src, uint32_t n, uint32_t bar) {
    asm volatile("cp.async.bulk.shared::cluster.global.mbarrier::complete_tx::bytes [%0], [%1], %2, [%3];" ::"r"(dst), "l"(src), "r"(n), "r"(bar) : "memory");
}
__device__ __forceinline__ void bulk_st(void* dst, uint32_t src, uint32_t n) {
    asm volatile("cp.async.bulk.global.shared::cta.bulk_group [%0], [%1], %2;" ::"l"(dst), "r"(src), "r"(n) : "memory");
}
__device__ __forceinline__ void bulk_commit() { asm volatile("cp.async.bulk.commit_group;" ::: "memory"); }
__device__ __forceinline__ void bulk_wait_read() { asm volatile("cp.async.bulk.wait_group.read 0;" ::: "memory"); }
__device__ __forceinline__ void bulk_wait_all() { asm volatile("cp.async.bulk.wait_group 0;" ::: "memory"); }
__device__ __forceinline__ void stsm4(uint32_t a, uint32_t r0, uint32_t r1, uint32_t r2, uint32_t r3) {
    asm volatile("stmatrix.sync.aligned.m8n8.x4.shared.b16 [%0], {%1,%2,%3,%4};" ::"r"(a), "r"(r0), "r"(r1), "r"(r2), "r"(r3) : "memory");
}
__device__ __forceinline__ void sts128(uint32_t a, uint32_t r0, uint32_t r1, uint32_t r2, uint32_t r3) {
    asm volatile("st.shared.v4.b32 [%0], {%1,%2,%3,%4};" ::"r"(a), "r"(r0), "r"(r1), "r"(r2), "r"(r3) : "memory");
}
__device__ __forceinline__ void lds128f(uint32_t a, float& x, float& y, float& z, float& u) { asm volatile("ld.shared.v4.f32 {%0,%1,%2,%3}, [%4];" : "=f"(x), "=f"(y), "=f"(z), "=f"(u) : "r"(a) : "memory"); }
__device__ __forceinline__ uint4 ldtab(int word) { return __ldg((const uint4*)(g_tab + word)); }
__device__ __forceinline__ void load_tw(cf (&tw)[8], int k1) {
#pragma unroll
    for (int i = 0; i < 4; i++) {
        const uint4 v = ldtab(TAB_TW + k1 * 16 + i * 4);
        tw[2 * i] = {__uint_as_float(v.x), __uint_as_float(v.y)};
        tw[2 * i + 1] = {__uint_as_float(v.z), __uint_as_float(v.w)};
    }
}
__device__ __forceinline__ void load_T(cf (&T)[8], int t7) {
#pragma unroll
    for (int i = 0; i < 4; i++)
        asm volatile("ld.global.nc.v4.f32 {%0,%1,%2,%3}, [%4];" : "=f"(T[2 * i].x), "=f"(T[2 * i].y), "=f"(T[2 * i + 1].x), "=f"(T[2 * i + 1].y) : "l"(g_tab + TAB_T + i * 512 + t7 * 4));
}
__device__ __forceinline__ float lds_bf(uint32_t a) { unsigned short v; asm volatile("ld.shared.u16 %0, [%1];" : "=h"(v) : "r"(a)); return __uint_as_float((uint32_t)v << 16); }
__device__ __forceinline__ unsigned get_epoch(uint32_t bars) {
    mbar_wait(bars + B_EP, 0);
    unsigned e;
    asm volatile("ld.shared.u32 %0, [%1];" : "=r"(e) : "r"(bars + B_EPOCH) : "memory");
    return e;
}
__device__ __forceinline__ void sts64f(uint32_t a, float x, float y) { asm volatile("st.shared.v2.f32 [%0], {%1,%2};" ::"r"(a), "f"(x), "f"(y) : "memory"); }
__device__ __forceinline__ uint32_t pk(float lo, float hi) { uint32_t r; asm("cvt.rn.bf16x2.f32 %0, %1, %2;" : "=r"(r) : "f"(hi), "f"(lo)); return r; }
__device__ __forceinline__ float bf2f(unsigned short v) { return __uint_as_float((uint32_t)v << 16); }

__device__ __forceinline__ uint64_t mkdesc(uint32_t addr, uint32_t lbo, uint32_t sbo, uint32_t swz) {
    return (uint64_t)((addr & 0x3FFFF) >> 4) | ((uint64_t)(lbo >> 4) << 16) | ((uint64_t)(sbo >> 4) << 32) | ((uint64_t)swz << 62);
}
__device__ __forceinline__ uint64_t opaque(uint64_t v) { asm volatile("" : "+l"(v)); return v; }
__device__ __forceinline__ void wg_fence() { asm volatile("wgmma.fence.sync.aligned;" ::: "memory"); }
__device__ __forceinline__ void wg_commit() { asm volatile("wgmma.commit_group.sync.aligned;" ::: "memory"); }
template <int N> __device__ __forceinline__ void wg_wait() { asm volatile("wgmma.wait_group.sync.aligned %0;" ::"n"(N) : "memory"); }
template <int N> __device__ __forceinline__ void pin(float (&d)[N]) {
#pragma unroll
    for (int i = 0; i < N; i++) asm volatile("" : "+f"(d[i])::"memory");
}
template <int N> __device__ __forceinline__ void pinu(uint32_t (&d)[N]) {
#pragma unroll
    for (int i = 0; i < N; i++) asm volatile("" : "+r"(d[i])::"memory");
}

#define R8(d, o) "+f"(d[o]), "+f"(d[o + 1]), "+f"(d[o + 2]), "+f"(d[o + 3]), "+f"(d[o + 4]), "+f"(d[o + 5]), "+f"(d[o + 6]), "+f"(d[o + 7])
#define L8 "%0,%1,%2,%3,%4,%5,%6,%7"
#define L32 L8 ",%8,%9,%10,%11,%12,%13,%14,%15,%16,%17,%18,%19,%20,%21,%22,%23,%24,%25,%26,%27,%28,%29,%30,%31"
#define L56 L32 ",%32,%33,%34,%35,%36,%37,%38,%39,%40,%41,%42,%43,%44,%45,%46,%47,%48,%49,%50,%51,%52,%53,%54,%55"
#define L64 L56 ",%56,%57,%58,%59,%60,%61,%62,%63"

template <int O, int TA, int TB, int N> __device__ __forceinline__ void mma128_ss(float (&d)[N], uint64_t da, uint64_t db, int sc) {
    asm volatile("{.reg .pred p; setp.ne.b32 p, %66, 0;\n"
                 "wgmma.mma_async.sync.aligned.m64n128k16.f32.bf16.bf16 {" L64 "}, %64, %65, p, 1, 1, %67, %68;}"
                 : R8(d, O), R8(d, O + 8), R8(d, O + 16), R8(d, O + 24), R8(d, O + 32), R8(d, O + 40), R8(d, O + 48), R8(d, O + 56)
                 : "l"(da), "l"(db), "r"(sc), "n"(TA), "n"(TB));
}
template <int TB> __device__ __forceinline__ void mma128_rs(float (&d)[64], uint32_t a0, uint32_t a1, uint32_t a2, uint32_t a3, uint64_t db, int sc) {
    asm volatile("{.reg .pred p; setp.ne.b32 p, %69, 0;\n"
                 "wgmma.mma_async.sync.aligned.m64n128k16.f32.bf16.bf16 {" L64 "}, {%64,%65,%66,%67}, %68, p, 1, 1, %70;}"
                 : R8(d, 0), R8(d, 8), R8(d, 16), R8(d, 24), R8(d, 32), R8(d, 40), R8(d, 48), R8(d, 56)
                 : "r"(a0), "r"(a1), "r"(a2), "r"(a3), "l"(db), "r"(sc), "n"(TB));
}
template <int TB> __device__ __forceinline__ void mma64_rs(float (&d)[32], uint32_t a0, uint32_t a1, uint32_t a2, uint32_t a3, uint64_t db, int sc) {
    asm volatile("{.reg .pred p; setp.ne.b32 p, %37, 0;\n"
                 "wgmma.mma_async.sync.aligned.m64n64k16.f32.bf16.bf16 {" L32 "}, {%32,%33,%34,%35}, %36, p, 1, 1, %38;}"
                 : R8(d, 0), R8(d, 8), R8(d, 16), R8(d, 24)
                 : "r"(a0), "r"(a1), "r"(a2), "r"(a3), "l"(db), "r"(sc), "n"(TB));
}
__device__ __forceinline__ void mma112_ss(float (&d)[64], uint64_t da, uint64_t db, int sc) {
    asm volatile("{.reg .pred p; setp.ne.b32 p, %58, 0;\n"
                 "wgmma.mma_async.sync.aligned.m64n112k16.f32.bf16.bf16 {" L56 "}, %56, %57, p, 1, 1, 0, 1;}"
                 : R8(d, 8), R8(d, 16), R8(d, 24), R8(d, 32), R8(d, 40), R8(d, 48), R8(d, 56)
                 : "l"(da), "l"(db), "r"(sc));
}
__device__ __forceinline__ void mma16_rs(float (&d)[64], uint32_t a0, uint32_t a1, uint32_t a2, uint32_t a3, uint64_t db, int sc) {
    asm volatile("{.reg .pred p; setp.ne.b32 p, %13, 0;\n"
                 "wgmma.mma_async.sync.aligned.m64n16k16.f32.bf16.bf16 {" L8 "}, {%8,%9,%10,%11}, %12, p, 1, 1, 1;}"
                 : R8(d, 0)
                 : "r"(a0), "r"(a1), "r"(a2), "r"(a3), "l"(db), "r"(sc));
}

__device__ __forceinline__ cf cmul(cf a, cf b) { return {fmaf(a.x, b.x, -a.y * b.y), fmaf(a.x, b.y, a.y * b.x)}; }
__device__ __forceinline__ cf cmulc(cf a, cf b) { return {fmaf(a.x, b.x, a.y * b.y), fmaf(a.y, b.x, -a.x * b.y)}; }
__device__ __forceinline__ cf cfma(cf a, cf b, cf c) { return {fmaf(a.x, b.x, fmaf(-a.y, b.y, c.x)), fmaf(a.x, b.y, fmaf(a.y, b.x, c.y))}; }
__device__ __forceinline__ cf cadd(cf a, cf b) { return {a.x + b.x, a.y + b.y}; }
__device__ __forceinline__ cf csub(cf a, cf b) { return {a.x - b.x, a.y - b.y}; }
__device__ __forceinline__ cf twice_minus(cf a, cf s) { return {fmaf(2.f, a.x, -s.x), fmaf(2.f, a.y, -s.y)}; }
__device__ __forceinline__ cf twid(int m, int M) {
    int r = ((m + M / 2) & (M - 1)) - M / 2;
    float s, c;
    __sincosf((float)r * (-6.283185307179586f / (float)M), &s, &c);
    return {c, s};
}
template <bool TW> __device__ __forceinline__ void dft8(cf (&v)[8], const cf (&tw)[8]) {
    const float s = 0.70710678118654752f;
    cf a0, a1, a2, a3, a4, a5, a6, a7;
    if (TW) {
        const cf t1 = cmul(v[1], tw[1]), t2 = cmul(v[2], tw[2]), t3 = cmul(v[3], tw[3]);
        a0 = cfma(v[4], tw[4], v[0]); a1 = twice_minus(v[0], a0);
        a2 = cfma(v[6], tw[6], t2); a3 = twice_minus(t2, a2);
        a4 = cfma(v[5], tw[5], t1); a5 = twice_minus(t1, a4);
        a6 = cfma(v[7], tw[7], t3); a7 = twice_minus(t3, a6);
    } else {
        a0 = cadd(v[0], v[4]); a1 = csub(v[0], v[4]); a2 = cadd(v[2], v[6]); a3 = csub(v[2], v[6]);
        a4 = cadd(v[1], v[5]); a5 = csub(v[1], v[5]); a6 = cadd(v[3], v[7]); a7 = csub(v[3], v[7]);
    }
    cf e0 = cadd(a0, a2), e2 = csub(a0, a2), e1 = {a1.x + a3.y, a1.y - a3.x}, e3 = {a1.x - a3.y, a1.y + a3.x};
    cf o0 = cadd(a4, a6), o2 = csub(a4, a6), o1 = {a5.x + a7.y, a5.y - a7.x}, o3 = {a5.x - a7.y, a5.y + a7.x};
    cf t1 = {o1.x + o1.y, o1.y - o1.x}, t3 = {o3.y - o3.x, -o3.x - o3.y};
    v[0] = cadd(e0, o0); v[4] = csub(e0, o0);
    v[1] = {fmaf(s, t1.x, e1.x), fmaf(s, t1.y, e1.y)}; v[5] = {fmaf(-s, t1.x, e1.x), fmaf(-s, t1.y, e1.y)};
    v[2] = {e2.x + o2.y, e2.y - o2.x}; v[6] = {e2.x - o2.y, e2.y + o2.x};
    v[3] = {fmaf(s, t3.x, e3.x), fmaf(s, t3.y, e3.y)}; v[7] = {fmaf(-s, t3.x, e3.x), fmaf(-s, t3.y, e3.y)};
}

__device__ __forceinline__ void bid2tile(int b, int& tc, int& cb) {
    int g, t;
    const int c = b >> 1;
    if (c < 4) { g = 0; t = 4 + c; }
    else if (c < 36) { g = (c + 3) & 7; t = (c - 4) >> 3; }
    else { g = 1 + (c - 30) % 7; t = 4 + (c - 36) / 7; }
    cb = t;
    tc = 2 * g + (b & 1);
}
__device__ __forceinline__ int pos_of(int n) { return (n & 24) + 4 * (n & 1) + ((n >> 1) & 3); }
__device__ __forceinline__ int kappa_of(int sig) {
    int k1 = sig & 31, r = sig >> 5;
    return k1 ? k1 + 64 * r : (r < 4 ? 64 * r : 32 + 64 * (r - 4));
}
__device__ __forceinline__ int slot3_of(int kap, int& cj) {
    int m = kap & 15;
    cj = (m > 8) || ((m & 7) == 0 && kap > 256);
    int kk = cj ? 512 - kap : kap;
    m = kk & 15;
    if (kk == 256) return 0;
    return m == 0 ? pos_of(kk >> 4) : (m == 8 ? pos_of(16 + (kk >> 4)) : m * 32 + pos_of(kk >> 4));
}

template <int NS> __device__ __forceinline__ uint32_t tags_bad(uint32_t buf, uint32_t tag, int t7) {
    uint32_t bad = 0;
#pragma unroll
    for (int i = 0; i < NS; i++) {
        uint32_t v;
        asm volatile("ld.shared.u32 %0, [%1];" : "=r"(v) : "r"(buf + t7 * 32 + (((t7 >> 2) & 1) << 4) + i * 4096) : "memory");
        bad |= v ^ tag;
    }
    return bad & 1;
}
__device__ __forceinline__ bool wg_all_ok(uint32_t bad, int id) {
    uint32_t ok;
    asm volatile("{.reg .pred p, q; setp.eq.u32 q, %1, 0; barrier.red.and.aligned.pred p, %2, 128, q; selp.u32 %0, 1, 0, p;}" : "=r"(ok) : "r"(bad), "r"(id) : "memory");
    return ok != 0;
}
__device__ __forceinline__ void load_w_rows(uint32_t dst, const CUtensorMap* mr, const CUtensorMap* mi, int kap, uint32_t bar) {
    mbar_expect_tx(bar, 8 * WPITCH);
    tma2d(dst, mr, (kap * 1026 >> 4) * 2, 0, bar);
    tma2d(dst + 4 * WPITCH, mi, (kap * 1026 >> 4) * 2, 0, bar);
}
__device__ __forceinline__ void prefetch_w_rows(const CUtensorMap* mr, const CUtensorMap* mi, int kap) {
    asm volatile("cp.async.bulk.prefetch.tensor.2d.L2.global [%0, {%1,%2}];" ::"l"(mr), "r"((kap * 1026 >> 4) * 2), "r"(0) : "memory");
    asm volatile("cp.async.bulk.prefetch.tensor.2d.L2.global [%0, {%1,%2}];" ::"l"(mi), "r"((kap * 1026 >> 4) * 2), "r"(0) : "memory");
}
#define SB0 1024
#define RDESC(off) (0x4000004000010000ull + (uint64_t)(SB0 / 16 + (off)))
template <int O, int TA, int SC, int DA, int DB> __device__ __forceinline__ void mma_g(float (&d)[128]) {
    asm volatile("{.reg .b64 da, db; mov.b64 da, %64; mov.b64 db, %65;\n"
                 "wgmma.mma_async.sync.aligned.m64n128k16.f32.bf16.bf16 {" L64 "}, da, db, %66, 1, 1, %67, 0;}"
                 : R8(d, O), R8(d, O + 8), R8(d, O + 16), R8(d, O + 24), R8(d, O + 32), R8(d, O + 40), R8(d, O + 48), R8(d, O + 56)
                 : "n"(RDESC(DA)), "n"(RDESC(DB)), "n"(SC), "n"(TA));
}
struct Ring {
    uint32_t full, rel;
    bool sig;
};
__device__ __forceinline__ void ring_release(const Ring& r, int slot) {
    if (r.sig) asm volatile("mbarrier.arrive.shared::cluster.b64 _, [%0];" ::"r"(r.rel + 8 * slot) : "memory");
}
__device__ __forceinline__ void peek(uint32_t a, uint32_t ph) { asm volatile("mbarrier.test_wait.parity.shared::cta.b64 pk, [%0], %1;" ::"r"(a), "r"(ph) : "memory"); }
__device__ __forceinline__ void peek_wait(uint32_t a, uint32_t ph) {
    asm volatile("{.reg .u32 n; @pk bra DONE; mov.u32 n, 0;\n"
                 "LOOP: mbarrier.try_wait.parity.shared::cta.b64 pk, [%0], %1; @pk bra DONE; add.u32 n, n, 1; setp.gt.u32 pk, n, %2; @!pk bra LOOP;\n"
                 "DONE: }" ::"r"(a), "r"(ph), "n"(SPIN_LIMIT) : "memory");
}
template <int TA, int SC, int SLOT, int HAND> __device__ __forceinline__ void gemm_step(float (&d)[128], Ring& r, uint32_t nph, bool rel, bool hand = false) {
    const int KA = TA ? 128 : 2, NX = (SLOT + 1) % NST;
    const int a = SLOT * 2048;
    wg_fence();
    mma_g<0, TA, SC, a, a + 1024>(d);
    mma_g<64, TA, SC, a + 512, a + 1024>(d);
    wg_commit();
    wg_wait<1>();
    if (rel) ring_release(r, (SLOT + NST - 1) % NST);
    mma_g<0, TA, 1, a + KA, a + 1026>(d);
    peek(r.full + 8 * NX, nph);
    mma_g<64, TA, 1, a + 512 + KA, a + 1026>(d);
    mma_g<0, TA, 1, a + 2 * KA, a + 1028>(d);
    mma_g<64, TA, 1, a + 512 + 2 * KA, a + 1028>(d);
    mma_g<0, TA, 1, a + 3 * KA, a + 1030>(d);
    if (HAND && hand) bar_arrive(HAND, 256);
    mma_g<64, TA, 1, a + 512 + 3 * KA, a + 1030>(d);
    wg_commit();
    if (!(HAND == 1 || HAND == 2) || !hand) peek_wait(r.full + 8 * NX, nph);
}
template <int K0> __device__ __forceinline__ void gemm1(float (&d)[128], Ring& r) {
#define PH(k) ((((k) / NST) & 1))
    mbar_wait_fast(r.full + 8 * (K0 % NST), PH(K0));
    gemm_step<0, 0, K0 % NST, 0>(d, r, PH(K0 + 1), false);
#pragma unroll 1
    for (int it = 0; it < 3; it++) {
        const uint32_t f = it & 1;
        gemm_step<0, 1, (K0 + 1) % NST, 0>(d, r, PH(K0 + 2) ^ f, true);
        gemm_step<0, 1, (K0 + 2) % NST, K0 ? 5 : 0>(d, r, PH(K0 + 3) ^ f, true, it == 2);
        gemm_step<0, 1, (K0 + 3) % NST, 0>(d, r, PH(K0 + 4) ^ f, true);
        gemm_step<0, 1, (K0 + 4) % NST, 0>(d, r, PH(K0 + 5) ^ f, true);
        gemm_step<0, 1, (K0 + 5) % NST, K0 ? 2 : 1>(d, r, PH(K0 + 6) ^ f, true, it == 2);
    }
}
__device__ __forceinline__ Ring ring_at(uint32_t sb, int k) {
    Ring r;
    r.full = sb + OFF_BAR + B_FULL;
    asm("mapa.shared::cluster.u32 %0, %1, %2;" : "=r"(r.rel) : "r"(sb + OFF_BAR + B_EMPTY), "r"((threadIdx.x >> 5) & 1));
    r.sig = (threadIdx.x & 95) == 0;
    return r;
}

__global__ void __cluster_dims__(2, 1, 1) __launch_bounds__(512, 1)
fused_kernel(const __grid_constant__ CUtensorMap tmX, const __grid_constant__ CUtensorMap tmBre, const __grid_constant__ CUtensorMap tmBim,
             const __grid_constant__ CUtensorMap tmCre, const __grid_constant__ CUtensorMap tmCim, const __grid_constant__ CUtensorMap tmXd,
             const __grid_constant__ CUtensorMap tmUst, const __grid_constant__ CUtensorMap tmVst,
             const __grid_constant__ CUtensorMap tmWr, const __grid_constant__ CUtensorMap tmWi,
             const __grid_constant__ CUtensorMap tmXA, const Params p) {
    extern __shared__ __align__(1024) uint8_t smraw[];
    const uint32_t sb = smem_u32(smraw);
    asm volatile(".reg .pred pk;");
    if ((sb & 0xFFFFFF) != SB0) return;
    const uint32_t bars = sb + OFF_BAR;
    const int tid = threadIdx.x, bid = blockIdx.x;
    const int wg = __shfl_sync(~0u, tid >> 7, 0), w = __shfl_sync(~0u, tid >> 5, 0) & 3, lane = tid & 31, g = lane >> 2, q = lane & 3;
    const bool extra = bid >= 128;
    int tc = 0, cb = 0;
    if (!extra) bid2tile(bid, tc, cb);
    const int fb = bid >> 5, fcb = bid & 31, fpos = pos_of(fcb);

    if (wg == 3) {
        asm volatile("setmaxnreg.dec.sync.aligned.u32 24;");
        if (w == 2) {
            if (lane < 4) asm volatile("prefetch.tensormap [%0];" ::"l"(lane == 0 ? &tmX : (lane == 1 ? &tmBre : (lane == 2 ? &tmBim : &tmXA))) : "memory");
        } else if (elect_one()) {
            if (w == 0) {
#pragma unroll
                for (int s = 0; s < NST; s++) { mbar_init(bars + B_FULL + s * 8, 1); mbar_init(bars + B_EMPTY + s * 8, 2); }
                mbar_init(bars + B_XIN, 1); mbar_init(bars + B_XIN + 8, 1); mbar_init(bars + B_QRD, 1);
            } else if (w == 1) {
#pragma unroll
                for (int o = B_HRDY; o < B_WSP; o += 8) mbar_init(bars + o, (o == B_LAM || o == B_STG) ? 4 : (o == B_STGU ? 8 : (o == B_QFREE ? QFREE_N : 1)));
            } else {
#pragma unroll
                for (int o = B_WSP; o < B_EPOCH; o += 8) if (o < B_XIN || o >= B_VIN) mbar_init(bars + o, (o >= B_WFREE && o < B_WD) ? 4 : 1);
            }
            asm volatile("fence.mbarrier_init.release.cluster;" ::: "memory");
            fence_async_sm();
        }
        __syncwarp();
        asm volatile("barrier.cluster.arrive.relaxed.aligned;" ::: "memory");
        if (w == 0 && !extra) {
            if (elect_one()) {
                mbar_expect_tx(bars + B_XIN, 16384);
                mbar_expect_tx(bars + B_XIN + 8, 16384);
#pragma unroll 1
                for (int k = 0; k < 2; k++) {
                    mbar_expect_tx(bars + B_FULL + k * 8, 32768);
                    tma5d(sb + k * 32768 + 16384, &tmX, k * 64, 0, 0, 0, tc, bars + B_FULL + k * 8);
                    if (k == 0) {
                        tma2d(sb + k * 32768, &tmBre, k * 64, cb * 64, bars + B_FULL + k * 8);
                        tma2d(sb + k * 32768 + 8192, &tmBim, k * 64, cb * 64, bars + B_FULL + k * 8);
                    }
                }
            }
            __syncwarp();
        }
        asm volatile("barrier.cluster.wait.aligned;" ::: "memory");
        if (bid == 129) return;
        if (w == 0) {
            if (!extra && elect_one()) {
                int s = 0, ph = 0;
                const int rank = bid & 1;
                STAMP(56);
#pragma unroll 1
                for (int k = 0; k < NST; k++) {
                    if (k >= 2) mbar_expect_tx(bars + B_FULL + k * 8, 32768);
                    if (k > 0) tma2d_mc(sb + k * 32768 + rank * 8192, rank ? &tmBim : &tmBre, k * 64, cb * 64, bars + B_FULL + k * 8);
                    if (k >= 2) tma5d(sb + k * 32768 + 16384, &tmX, k * 64, 0, 0, 0, tc, bars + B_FULL + k * 8);
                }
#pragma unroll 1
                for (int i = 0; i < 2; i++) tma4d(sb + OFF_F + i * 4096, &tmXA, fcb * 32 + (i >> 2) * 16, 0, (i & 3) * 2, fb, bars + B_XIN + (i >> 2) * 8);
#pragma unroll 1
                for (int k = NST; k < 65; k++) {
                    const uint32_t fbar = bars + B_FULL + s * 8, a = sb + s * 32768;
                    mbar_wait(bars + B_EMPTY + s * 8, ph);
                    mbar_expect_tx(fbar, 32768);
                    if (k < 32) {
                        const int kk = (k & 15) * 64;
                        tma2d_mc(a + rank * 8192, rank ? &tmBim : &tmBre, kk, (k >> 4) * 512 + cb * 64, fbar);
                        tma5d(a + 16384, &tmX, kk, 0, 0, 0, tc, fbar);
                    } else if (k == 32) {
                        tma2d(a, &tmXd, cb * 128, tc * 128, fbar);
                        tma2d(a + 16384, &tmXd, cb * 128 + 64, tc * 128, fbar);
                    } else {
                        const int kk = k - 33, ri = (kk >> 3) & 1, blk = ((kk >> 4) << 3) | (kk & 7);
                        tma2d_mc(a + 16384 + rank * 8192, ri ? &tmCim : &tmCre, blk * 64, cb * 128 + rank * 64, fbar);
                        if ((kk & 7) == 0) { mbar_wait(bars + B_HRDY + kk, 0); STAMPR(45 + (kk >> 3)); }
                        bulk_ld(a, g_H + (size_t)(tc * 32 + blk * 2 + ri) * 16384, 16384, fbar);
                    }
                    if (k < NST + 6) {
                        const int i = k - NST + 2;
                        tma4d(sb + OFF_F + i * 4096, &tmXA, fcb * 32 + (i >> 2) * 16, 0, (i & 3) * 2, fb, bars + B_XIN + (i >> 2) * 8);
                    }
                    if (k == LDK) mbar_arrive(bars + B_LDONE);
                    if (++s == NST) { s = 0; ph ^= 1; }
                }
            }
        } else if (w == 1) {
          if (elect_one()) {
            unsigned ep;
            asm volatile("ld.relaxed.gpu.global.u32 %0, [%1];" : "=r"(ep) : "l"(g_epoch + bid * 8) : "memory");
            ep++;
            asm volatile("st.relaxed.gpu.global.u32 [%0], %1;" ::"l"(g_epoch + bid * 8), "r"(ep) : "memory");
            asm volatile("st.shared.u32 [%0], %1;" ::"r"(bars + B_EPOCH), "r"(ep) : "memory");
            mbar_arrive(bars + B_EP);
            if (!extra) mbar_wait(bars + B_STGU, 0);
            const int kap0 = extra ? 0 : kappa_of(bid * 2), kap1 = extra ? 256 : kappa_of(bid * 2 + 1);
            const uint8_t* usrc = g_U + (size_t)(extra ? 0 : bid * 32768);
            if (!extra) {
                STAMP(21);
#pragma unroll 1
                for (int r = 0; r < 256 / UBOX; r++) {
                    tma2d_st(&tmUst, fb * 2048 + fpos * 64, r * UBOX, sb + OFF_P + r * (UBOX * 128));
                    if (r == 256 / UBOX - 1) red_hint(g_cnt);
                    if (r < 256 / UBOX - 1) __nanosleep(PACE_U);
                }
                bulk_commit();
                bulk_wait_read();
                STAMP(40);
                STAMP(41);
            }
            mbar_expect_tx(bars + B_FG, 8192);
            bulk_ld(sb + OFF_F, g_tab + TAB_FG, 8192, bars + B_FG);
            wait_cnt(g_cnt, 128 * ep);
            STAMP(42);
            mbar_expect_tx(bars + B_UIN, 16384);
            bulk_ld(sb + OFF_P, usrc, 16384, bars + B_UIN);
            load_w_rows(sb + OFF_X, &tmWr, &tmWi, kap0, bars + B_WD);
            load_w_rows(sb + OFF_P + 16384, &tmWr, &tmWi, (512 - kap0) & 511, bars + B_WM);
            __nanosleep(1000);
            prefetch_w_rows(&tmWr, &tmWi, kap1);
            prefetch_w_rows(&tmWr, &tmWi, 512 - kap1);
            mbar_wait(bars + B_WFREE, 0);
            mbar_expect_tx(bars + B_UIN + 8, 16384);
            bulk_ld(sb + OFF_P + 16384, usrc + (extra ? 0 : 16384), 16384, bars + B_UIN + 8);
            load_w_rows(sb + OFF_X, &tmWr, &tmWi, kap1, bars + B_WD);
#pragma unroll 1
            for (int gi = 0; gi < 2; gi++) {
                mbar_wait(bars + B_STG, gi);
                STAMPR(23 + gi);
                if (extra ? (gi == 1) : (bid + gi != 0)) {
                    int cj;
                    const int s3 = extra ? 0 : slot3_of(gi ? kap1 : kap0, cj);
                    const uint32_t src = extra ? sb : sb + OFF_P + gi * 16384;
#pragma unroll 1
                    for (int r = 0; r < 256 / VBOX; r++) {
                        tma3d_st(&tmVst, s3 * 32, (r * VBOX) & 127, (r * VBOX) >> 7, src + r * (VBOX * 64));
                        if (r < 256 / VBOX - 1) __nanosleep(PACE_V);
                    }
                    bulk_commit();
                }
                if (gi == 0) { bulk_wait_read(); load_w_rows(sb + OFF_P, &tmWr, &tmWi, 512 - kap1, bars + B_WM); }
            }
            red_hint(g_cnt + 32);
            bulk_wait_read();
            STAMP(49);
            STAMP(43);
            if (!extra) {
                wait_cnt(g_cnt + 32, 129 * ep);
                STAMP(44);
                mbar_expect_tx(bars + B_VIN, 16384);
                bulk_ld(sb + OFF_P, g_V + (size_t)bid * 32768, 16384, bars + B_VIN);
                mbar_expect_tx(bars + B_VIN + 8, 16384);
                bulk_ld(sb + OFF_P + 16384, g_V + (size_t)bid * 32768 + 16384, 16384, bars + B_VIN + 8);
            }
          }
        } else if (w == 3) {
            if (!extra && elect_one()) {
                const unsigned ep = get_epoch(bars);
#pragma unroll 1
                for (int hh = 0; hh < 4; hh++) {
                    mbar_wait(bars + B_HOWN + hh * 8, 0);
                    bulk_st(g_H + (size_t)(tc * 32 + ((hh >> 1) * 8 + cb) * 2 + (hh & 1)) * 16384, sb + OFF_Q, 16384);
                    bulk_commit();
                    bulk_wait_all();
                    if (!(hh & 1)) mbar_arrive(bars + B_QRD);
                    else if (hh == 1) asm volatile("mbarrier.arrive.shared::cta.b64 _, [%0], %1;" ::"r"(bars + B_QFREE), "n"(QFREE_N) : "memory");
                    fence_async();
                    asm volatile("st.release.gpu.global.u32 [%0], %1;" ::"l"(g_hcnt + tc * 32 + hh * 8 + cb), "r"(ep) : "memory");
                    STAMPR(57 + hh);
                }
            }
        } else if (w == 2) {
            const int gi = lane >> 4, j = (lane >> 1) & 3, mir = (lane >> 3) & 1;
            const int kap = extra ? gi * 256 : kappa_of(bid * 2 + gi);
            const int r0 = kap + 512 * j, r1 = (2048 - r0) & 2047;
            const unsigned short* wp = (const unsigned short*)((lane & 1) ? p.wi : p.wr);
            const float a = bf2f(wp[r0 * 513 + mir * 512]), b = bf2f(wp[r1 * 513 + mir * 512]);
            asm volatile("st.shared.f32 [%0], %1;" ::"r"(sb + OFF_WSP + lane * 4), "f"(0.5f * ((lane & 1) ? a - b : a + b)) : "memory");
            __syncwarp();
            if (lane == 0) mbar_arrive(bars + B_WSP);
            if (!extra) {
                const unsigned ep = get_epoch(bars);
#pragma unroll 1
                for (int hh = 0; hh < 4; hh++) {
                    mbar_wait(bars + B_HOWN + hh * 8, 0);
                    unsigned n = 0;
                    while (!__all_sync(~0u, ld_rlx(g_hcnt + tc * 32 + hh * 8 + (lane & 7)) == ep) && ++n < SPIN_LIMIT) __nanosleep(20);
                    if (lane == 0) { fence_async(); mbar_arrive(bars + B_HRDY + hh * 8); }
                }
            }
        }
    } else {
        asm volatile("barrier.cluster.arrive.relaxed.aligned; barrier.cluster.wait.aligned;" ::: "memory");
        STAMP(55);
        asm volatile("setmaxnreg.inc.sync.aligned.u32 152;");
        if (extra && (wg != 2 || bid == 129)) return;
        const int t7 = tid & 127, hf = wg - 1;
        const int k1 = 8 * w + g;
        const int mi = lane >> 3, gl = lane & 7;
        const uint32_t tmask = q == 0 ? ~1u : ~0u;
        if (wg != 0 && !extra) {
            uint32_t f1[16];
#pragma unroll
            for (int j = 0; j < 4; j++) { const uint4 v = ldtab(TAB_F1 + j * 512 + t7 * 4); f1[4 * j] = v.x; f1[4 * j + 1] = v.y; f1[4 * j + 2] = v.z; f1[4 * j + 3] = v.w; }
            cf tw[8];
            load_tw(tw, k1);
            const uint32_t tbit = get_epoch(bars) & ~tmask;
            float acc[64];
            const uint64_t dx = opaque(mkdesc(sb + OFF_F + hf * 16384, 2048, 256, 3));
            mbar_wait(bars + B_XIN + hf * 8, 0);
            STAMP(20);
            pinu(f1);
            wg_fence();
#pragma unroll
            for (int j = 0; j < 4; j++)
                mma128_rs<1>(acc, f1[4 * j], f1[4 * j + 1], f1[4 * j + 2], f1[4 * j + 3], dx + j * 32, j);
            wg_commit();
            wg_wait<0>();
            pin(acc);
            pinu(f1);
            if (hf == 0) bar_sync(8, 128);
            else bar_sync(3, 128);
            if (k1 == 0) {
#pragma unroll
                for (int i = 0; i < 16; i++) {
                    const uint32_t a = sb + OFF_F + hf * 16384 + (i >> 1) * 64 + ((i & 1) * 8 + 2 * q) * 4;
                    sts64f(a, acc[4 * i], acc[4 * i + 1]);
                    sts64f(a + 512, acc[4 * i + 2], acc[4 * i + 3]);
                }
            }
            uint4 fx0, fx1;
#pragma unroll
            for (int cl = 0; cl < 2; cl++) {
                if (cl == 1) {
                    asm volatile("ld.global.nc.v4.b32 {%0,%1,%2,%3}, [%4];" : "=r"(fx0.x), "=r"(fx0.y), "=r"(fx0.z), "=r"(fx0.w) : "l"(g_tab + TAB_FX + ((t7 >> 2) & 15) * 8));
                    asm volatile("ld.global.nc.v4.b32 {%0,%1,%2,%3}, [%4];" : "=r"(fx1.x), "=r"(fx1.y), "=r"(fx1.z), "=r"(fx1.w) : "l"(g_tab + TAB_FX + ((t7 >> 2) & 15) * 8 + 4));
                }
                cf v0[8], v1[8];
#pragma unroll
                for (int n = 0; n < 8; n++) {
                    const int i = 4 * (2 * n + cl);
                    v0[n] = {acc[i], acc[i + 2]};
                    v1[n] = {acc[i + 1], acc[i + 3]};
                }
                dft8<true>(v0, tw);
                dft8<true>(v1, tw);
                const uint32_t a0 = sb + OFF_P + (8 * w + gl + 32 * (mi >> 1)) * 128 + (((((mi & 1) << 2) | ((2 * hf + cl) ^ (fpos & 3))) ^ gl) << 4);
#pragma unroll
                for (int r = 0; r < 8; r += 2) {
                    uint32_t o0 = pk(v0[r].x, v1[r].x), o1 = pk(v0[r].y, v1[r].y), o2 = pk(v0[r + 1].x, v1[r + 1].x), o3 = pk(v0[r + 1].y, v1[r + 1].y);
                    if (cl == 0) { o0 = (o0 & tmask) | tbit; o1 = (o1 & tmask) | tbit; o2 = (o2 & tmask) | tbit; o3 = (o3 & tmask) | tbit; }
                    stsm4(a0 + r * 4096, o0, o1, o2, o3);
                }
            }
            if (hf == 0) bar_sync(8, 128);
            else bar_sync(3, 128);
            if (t7 & 64) {
                const int o = (t7 >> 2) & 15, r = o >> 1, ri = o & 1, cg = t7 & 3;
                float s0 = 0.f, s1 = 0.f, s2 = 0.f, s3 = 0.f;
#pragma unroll
                for (int n = 0; n < 8; n++) {
                    const float c = __uint_as_float(n < 4 ? (n == 0 ? fx0.x : n == 1 ? fx0.y : n == 2 ? fx0.z : fx0.w) : (n == 4 ? fx1.x : n == 5 ? fx1.y : n == 6 ? fx1.z : fx1.w));
                    float x0, x1, x2, x3;
                    lds128f(sb + OFF_F + hf * 16384 + (r < 4 ? 0 : 512) + n * 64 + cg * 16, x0, x1, x2, x3);
                    s0 = fmaf(c, x0, s0); s1 = fmaf(c, x1, s1); s2 = fmaf(c, x2, s2); s3 = fmaf(c, x3, s3);
                }
                asm volatile("st.shared.v2.b32 [%0], {%1,%2};" ::"r"(sb + OFF_P + r * 4096 + ((ri * 4 + ((2 * hf + (cg >> 1)) ^ (fpos & 3))) << 4) + (cg & 1) * 8), "r"((pk(s0, s1) & tmask) | tbit), "r"(pk(s2, s3)) : "memory");
            }
            fence_async_sm();
            __syncwarp();
            if (lane == 0) { mbar_arrive(bars + B_STGU); mbar_arrive(bars + B_QFREE); }
        }
        if (wg != 2) {
        if (wg == 0) bar_sync(4, 128);
        asm volatile("setmaxnreg.inc.sync.aligned.u32 168;");
        const int ch0 = wg * 512 + cb * 64;
        if (wg == 1) {
            const int cl = tid & 127, ch = (cl >> 6) * 512 + cb * 64 + (cl & 63);
            const float lr = __bfloat162float(p.lre[ch]), li = __bfloat162float(p.lim[ch]);
            const float dt = __bfloat162float(__float2bfloat16(expf(__bfloat162float(p.ldt[ch]))));
            float sn, cs;
            sincosf(dt * li, &sn, &cs);
            const float ex = expf(dt * lr), br = ex * cs, bi = ex * sn;
            const float inv = 2.0f / (lr * lr + li * li);
            const float cr = ((br - 1.f) * lr + bi * li) * inv, ci = (bi * lr - (br - 1.f) * li) * inv;
            sts128(sb + OFF_LAM + cl * 16, __float_as_uint(br), __float_as_uint(-bi), __float_as_uint(cr), __float_as_uint(-ci));
            __syncwarp();
            if (lane == 0) mbar_arrive(bars + B_LAM);
        }
        float d[128];
        if (wg == 1) bar_sync(1, 256);
        STAMPW(0, 10);
        Ring rg = ring_at(sb, wg * 16);
        if (wg == 0) gemm1<0>(d, rg); else gemm1<16>(d, rg);
        cf lam[2], gam[2], lam2[2];
        const uint32_t lama = sb + OFF_LAM + wg * 1024 + (16 * w + g) * 16;
        mbar_wait(bars + B_LAM, 0);
        const unsigned ep = get_epoch(bars);
        mbar_wait(bars + B_QFREE, wg);
        asm volatile("ld.shared.v2.f32 {%0,%1}, [%2];" : "=f"(lam[0].x), "=f"(lam[0].y) : "r"(lama) : "memory");
        asm volatile("ld.shared.v2.f32 {%0,%1}, [%2];" : "=f"(lam[1].x), "=f"(lam[1].y) : "r"(lama + 128) : "memory");
        asm volatile("ld.shared.v2.f32 {%0,%1}, [%2];" : "=f"(lam2[0].x), "=f"(lam2[0].y) : "r"(lama + ((lane & 7) - g) * 16) : "memory");
        asm volatile("ld.shared.v2.f32 {%0,%1}, [%2];" : "=f"(lam2[1].x), "=f"(lam2[1].y) : "r"(lama + ((lane & 7) - g) * 16 + 128) : "memory");
#pragma unroll
        for (int i = 0; i < 7; i++) { lam2[0] = cmul(lam2[0], lam2[0]); lam2[1] = cmul(lam2[1], lam2[1]); }
        cf l16[2] = {lam[0], lam[1]};
#pragma unroll
        for (int i = 0; i < 4; i++) { l16[0] = cmul(l16[0], l16[0]); l16[1] = cmul(l16[1], l16[1]); }
        asm volatile("" : "+f"(lam2[0].x), "+f"(lam2[0].y), "+f"(lam2[1].x), "+f"(lam2[1].y), "+f"(l16[0].x), "+f"(l16[0].y), "+f"(l16[1].x), "+f"(l16[1].y)::"memory");
        wg_wait<0>();
        ring_release(rg, wg ? 31 % NST : 15 % NST);
        pin(d);
        STAMPW(1, 11);
        uint32_t dd[16];
        {
            cf f[2], fb2[2];
#pragma unroll
            for (int i = 0; i < 16; i++)
#pragma unroll
                for (int h = 0; h < 2; h++) {
                    const int r = 4 * (i >> 1) + 2 * h + (i & 1);
                    f[h] = i ? cfma(lam[h], f[h], {d[r], -d[64 + r]}) : cf{d[r], -d[64 + r]};
                    fb2[h] = i ? cfma(lam[h], fb2[h], {d[32 + r], -d[96 + r]}) : cf{d[32 + r], -d[96 + r]};
                }
            cf st[2], l32[2];
            uint4* cbase = g_carry + (ch0 >> 1) + 8 * w;
            const unsigned tag = ep & 15u;
#pragma unroll
            for (int h = 0; h < 2; h++) {
                cf L = l16[h];
                f[h] = cfma(L, f[h], fb2[h]);
                L = cmul(L, L);
                l32[h] = L;
                const cf v0 = {__shfl_sync(~0u, f[h].x, 0, 4), __shfl_sync(~0u, f[h].y, 0, 4)};
                const cf v1 = cfma(L, v0, {__shfl_sync(~0u, f[h].x, 1, 4), __shfl_sync(~0u, f[h].y, 1, 4)});
                const cf v2 = cfma(L, v1, {__shfl_sync(~0u, f[h].x, 2, 4), __shfl_sync(~0u, f[h].y, 2, 4)});
                f[h] = cfma(L, v2, f[h]);
                st[h] = (q & 2) ? ((q & 1) ? v2 : v1) : ((q & 1) ? v0 : cf{0.f, 0.f});
            }
            if (q == 3)
                asm volatile("{.reg .b64 a, b; mov.b64 a, {%1,%2}; mov.b64 b, {%3,%4}; st.relaxed.gpu.global.v2.b64 [%0], {a, b};}" ::"l"(cbase + g + tc * 512),
                             "r"((__float_as_uint(f[0].x) & ~15u) | tag), "r"((__float_as_uint(f[0].y) & ~15u) | tag),
                             "r"((__float_as_uint(f[1].x) & ~15u) | tag), "r"((__float_as_uint(f[1].y) & ~15u) | tag) : "memory");
            STAMPX(2, 12);
            asm volatile("ld.shared.v2.f32 {%0,%1}, [%2];" : "=f"(gam[0].x), "=f"(gam[0].y) : "r"(lama + 8) : "memory");
            asm volatile("ld.shared.v2.f32 {%0,%1}, [%2];" : "=f"(gam[1].x), "=f"(gam[1].y) : "r"(lama + 136) : "memory");
#pragma unroll
            for (int r = 0; r < 64; r++)
                asm volatile("{.reg .f32 s, t; mul.f32 s, %3, %1; mul.f32 t, %2, %1; neg.f32 t, t; fma.rn.f32 %1, %3, %0, t; fma.rn.f32 %0, %2, %0, s;}"
                             : "+f"(d[r]), "+f"(d[64 + r]) : "f"(gam[(r >> 1) & 1].x), "f"(gam[(r >> 1) & 1].y));
            st[0] = cmul(gam[0], st[0]);
            st[1] = cmul(gam[1], st[1]);
            cf lq[2];
#pragma unroll
            for (int h = 0; h < 2; h++) {
                const cf one = {1.f, 0.f}, L = l32[h], L2 = cmul(L, L);
                lq[h] = cmul(gam[h], cmul((q & 1) ? L : one, (q & 2) ? L2 : one));
            }
            const uint32_t park = sb + OFF_Q + w * 2048 + lane * 16;
            sts128(park, __float_as_uint(st[0].x), __float_as_uint(st[0].y), __float_as_uint(st[1].x), __float_as_uint(st[1].y));
            sts128(park + 512, __float_as_uint(lq[0].x), __float_as_uint(lq[0].y), __float_as_uint(lq[1].x), __float_as_uint(lq[1].y));
            {
                uint32_t fv[4][4];
                unsigned n = 0;
                bool ok;
                if (tc) __nanosleep(100);
                do {
                    asm volatile(
                        "{.reg .pred p0, p1, p2, p3; .reg .b64 a0, b0, a1, b1, a2, b2, a3, b3;\n"
                        "setp.ge.s32 p0, %17, 0; setp.ge.s32 p1, %17, 4; setp.ge.s32 p2, %17, 8; setp.ge.s32 p3, %17, 12;\n"
                        "mov.b64 a0, {%18,%18}; mov.b64 b0, a0; mov.b64 a1, a0; mov.b64 b1, a0; mov.b64 a2, a0; mov.b64 b2, a0; mov.b64 a3, a0; mov.b64 b3, a0;\n"
                        "@p0 ld.relaxed.gpu.global.v2.b64 {a0, b0}, [%16];\n"
                        "@p1 ld.relaxed.gpu.global.v2.b64 {a1, b1}, [%16+-32768];\n"
                        "@p2 ld.relaxed.gpu.global.v2.b64 {a2, b2}, [%16+-65536];\n"
                        "@p3 ld.relaxed.gpu.global.v2.b64 {a3, b3}, [%16+-98304];\n"
                        "mov.b64 {%0,%1}, a0; mov.b64 {%2,%3}, b0; mov.b64 {%4,%5}, a1; mov.b64 {%6,%7}, b1;\n"
                        "mov.b64 {%8,%9}, a2; mov.b64 {%10,%11}, b2; mov.b64 {%12,%13}, a3; mov.b64 {%14,%15}, b3;}"
                        : "=r"(fv[0][0]), "=r"(fv[0][1]), "=r"(fv[0][2]), "=r"(fv[0][3]), "=r"(fv[1][0]), "=r"(fv[1][1]), "=r"(fv[1][2]), "=r"(fv[1][3]),
                          "=r"(fv[2][0]), "=r"(fv[2][1]), "=r"(fv[2][2]), "=r"(fv[2][3]), "=r"(fv[3][0]), "=r"(fv[3][1]), "=r"(fv[3][2]), "=r"(fv[3][3])
                        : "l"(cbase + (lane & 7) + (tc - 1 - (lane >> 3)) * 512), "r"(tc - 1 - (lane >> 3)), "r"(tag) : "memory");
                    unsigned bad = 0;
#pragma unroll
                    for (int a = 0; a < 16; a++) bad |= fv[a >> 2][a & 3] ^ tag;
                    ok = (bad & 15u) == 0;
                } while (!__all_sync(~0u, ok) && ++n < SPIN_LIMIT);
                STAMPX(53, 54);
                lds128f(park, st[0].x, st[0].y, st[1].x, st[1].y);
                lds128f(park + 512, lq[0].x, lq[0].y, lq[1].x, lq[1].y);
                cf P[2];
#pragma unroll
                for (int h = 0; h < 2; h++) {
                    const cf one = {1.f, 0.f}, M = lam2[h], M2 = cmul(M, M), M4 = cmul(M2, M2);
                    P[h] = {__uint_as_float(fv[3][2 * h]), __uint_as_float(fv[3][2 * h + 1])};
#pragma unroll
                    for (int a = 2; a >= 0; a--) P[h] = cfma(M4, P[h], {__uint_as_float(fv[a][2 * h]), __uint_as_float(fv[a][2 * h + 1])});
                    P[h] = cmul(P[h], cmul((lane & 8) ? M : one, (lane & 16) ? M2 : one));
                }
#pragma unroll
                for (int h = 0; h < 2; h++) {
                    const float sx = (__shfl_sync(~0u, P[h].x, g) + __shfl_sync(~0u, P[h].x, g + 8)) + (__shfl_sync(~0u, P[h].x, g + 16) + __shfl_sync(~0u, P[h].x, g + 24));
                    const float sy = (__shfl_sync(~0u, P[h].y, g) + __shfl_sync(~0u, P[h].y, g + 8)) + (__shfl_sync(~0u, P[h].y, g + 16) + __shfl_sync(~0u, P[h].y, g + 24));
                    st[h] = cfma(lq[h], {sx, sy}, st[h]);
                }
            }
            STAMPX(3, 13);
            const uint32_t qa = sb + OFF_Q + w * 2048 + g * 128;
            uint32_t hp[32], hr[8];
#pragma unroll
            for (int i = 0; i < 16; i++)
#pragma unroll
                for (int h = 0; h < 2; h++) {
                    const int r = 4 * i + 2 * h;
                    const cf a = cfma(lam[h], st[h], {d[r], d[64 + r]});
                    st[h] = cfma(lam[h], a, {d[r + 1], d[64 + r + 1]});
                    hr[4 * h + (i & 3)] = pk(a.x, st[h].x);
                    hp[16 * h + i] = pk(a.y, st[h].y);
                    if ((i & 3) == 3) sts128(qa + (i >> 3) * 8192 + h * 1024 + (((2 * q + ((i >> 2) & 1)) ^ g) << 4), hr[4 * h], hr[4 * h + 1], hr[4 * h + 2], hr[4 * h + 3]);
                }
            STAMPW(4, 14);
            fence_async_sm();
            __syncwarp();
            if (lane == 0) mbar_arrive(bars + B_HOWN + wg * 16);
            STAMPW(51, 52);
#pragma unroll
            for (int i = 0; i < 16; i++) asm volatile("ld.global.nc.b32 %0, [%1];" : "=r"(dd[i]) : "l"((const uint32_t*)(p.dsk + cb * 128 + 2 * q) + 4 * i));
            mbar_wait(bars + B_QRD, wg);
#pragma unroll
            for (int j = 0; j < 8; j++) {
                const int r = 16 * ((j >> 1) & 1) + 8 * (j >> 2) + 4 * (j & 1);
                sts128(qa + (j >> 2) * 8192 + ((j >> 1) & 1) * 1024 + (((2 * q + (j & 1)) ^ g) << 4), hp[r], hp[r + 1], hp[r + 2], hp[r + 3]);
            }
            fence_async_sm();
            __syncwarp();
            if (lane == 0) mbar_arrive(bars + B_HOWN + wg * 16 + 8);
            STAMPW(5, 15);
        }
        if (wg == 0) {
            float y[128];
            bar_sync(5, 256);
            mbar_wait(bars + B_FULL + (32 % NST) * 8, (32 / NST) & 1);
            const uint32_t xa = sb + (32 % NST) * 32768 + (32 * w + lane) * 128;
#pragma unroll
            for (int c = 0; c < 16; c++) {
                uint32_t xx[4];
                asm volatile("ldmatrix.sync.aligned.m8n8.x4.shared.b16 {%0,%1,%2,%3}, [%4];" : "=r"(xx[0]), "=r"(xx[1]), "=r"(xx[2]), "=r"(xx[3])
                             : "r"(xa + (c >> 3) * 16384 + (((c & 7) ^ (lane & 7)) << 4)) : "memory");
#pragma unroll
                for (int r = 0; r < 4; r++) {
                    uint32_t pr;
                    asm("fma.rn.bf16x2 %0, %1, %2, %3;" : "=r"(pr) : "r"(xx[r]), "r"(dd[c]), "r"(0x80008000u));
                    y[64 * (r >> 1) + 4 * c + 2 * (r & 1)] = __uint_as_float(pr << 16);
                    y[64 * (r >> 1) + 4 * c + 2 * (r & 1) + 1] = __uint_as_float(pr & 0xffff0000u);
                }
            }
            bar_sync(4, 128);
            rg = ring_at(sb, 33);
            ring_release(rg, 32 % NST);
            mbar_wait(rg.full + (33 % NST) * 8, PH(33));
            pin(y);
            STAMP(6);
            bar_sync(2, 256);
            STAMP(7);
#pragma unroll 1
            for (int it = 0; it < 6; it++) {
                const uint32_t f = it & 1;
                gemm_step<1, 1, 33 % NST, 0>(y, rg, PH(34) ^ f, it != 0);
                gemm_step<1, 1, 34 % NST, 0>(y, rg, PH(35) ^ f, true);
                gemm_step<1, 1, 35 % NST, 0>(y, rg, PH(36) ^ f, true);
                gemm_step<1, 1, 36 % NST, 0>(y, rg, PH(37) ^ f, it != 5);
                gemm_step<1, 1, 37 % NST, 0>(y, rg, PH(38) ^ f, it != 5);
            }
#define HALF(O, k) mma_g<O, 1, 1, (k % NST) * 2048 + O * 8, (k % NST) * 2048 + 1024>(y); mma_g<O, 1, 1, (k % NST) * 2048 + O * 8 + 128, (k % NST) * 2048 + 1026>(y); \
                   mma_g<O, 1, 1, (k % NST) * 2048 + O * 8 + 256, (k % NST) * 2048 + 1028>(y); mma_g<O, 1, 1, (k % NST) * 2048 + O * 8 + 384, (k % NST) * 2048 + 1030>(y);
            wg_fence();
            peek(rg.full + (64 % NST) * 8, PH(64));
            HALF(0, 63)
            peek_wait(rg.full + (64 % NST) * 8, PH(64));
            wg_fence();
            HALF(0, 64)
            wg_commit();
            HALF(64, 63)
            HALF(64, 64)
            wg_commit();
#pragma unroll
            for (int r = 0; r < 4; r++) {
                if (r == 0) {
                    wg_wait<1>();
#pragma unroll
                    for (int i = 0; i < 64; i++) asm volatile("" : "+f"(y[i])::"memory");
                    STAMP(16);
                    bar_sync(4, 128);
                }
                if (r == 1) STAMP(17);
                if (r == 3) STAMP(19);
                if (r == 2) {
                    STAMP(18);
                    wg_wait<0>();
#pragma unroll
                    for (int i = 64; i < 128; i++) asm volatile("" : "+f"(y[i])::"memory");
                    STAMP(8);
                    bar_sync(4, 128);
                }
                const uint32_t stg = sb + (r >> 1) * (64 * 544) + w * (16 * 544);
#pragma unroll
                for (int c = 0; c < 16; c++) {
                    const int yi = 64 * (r >> 1) + 4 * c + 2 * (r & 1);
                    sts64f(stg + (8 * (r & 1) + g) * 544 + c * 32 + q * 8, y[yi], y[yi + 1]);
                }
                fence_async_sm();
                __syncwarp();
                if ((lane >> 3) == r) {
                    bulk_st(p.out + (size_t)(tc * 128 + 32 * w + lane) * 2048 + 1024 + cb * 128, stg + (lane & 15) * 544, 512);
                    bulk_commit();
                }
            }
            bulk_wait_read();
            STAMP(9);
            return;
        }
        bar_sync(8, 128);
        asm volatile("setmaxnreg.dec.sync.aligned.u32 152;");
        } else {
        {
            cf T[8];
            load_T(T, t7);
            const uint32_t tag = get_epoch(bars) & 1;
            mbar_wait(bars + B_WSP, 0);
            mbar_wait(bars + B_FG, 0);
#pragma unroll 1
            for (int gi = 0; gi < 2; gi++) {
                const int kap = extra ? gi * 256 : kappa_of(bid * 2 + gi);
                const uint32_t buf = sb + OFF_P + gi * 16384;
                STAMP3(39);
                const int kq = kap + 512 * q;
                const cf be1 = twid(kq, 2048), be2 = cmul(be1, be1), be3 = cmul(be1, be2);
                uint32_t wad[4];
#pragma unroll
                for (int j = 0; j < 4; j++) wad[j] = sb + OFF_X + ((j + q) & 3) * WPITCH + ((2 * kap) & 15) + 2 * k1 + 128 * q;
                float acc[64], za[32], zb[32], ya[32], yb[32], vv[64];
                const uint64_t dF = opaque(mkdesc(sb + OFF_F, 16, 1024, 1)), dB = opaque(mkdesc(buf, 4096, 512, 2));
#pragma unroll 1
                for (int n = 0; n < 4096; n++) {
                    mbar_wait(bars + B_UIN + gi * 8, n & 1);
                    STAMP3(22);
                    wg_fence();
#pragma unroll
                    for (int j = 0; j < 4; j++) mma128_ss<0, 0, 1>(acc, dF + j * 2, dB + j * 64, j);
                    wg_commit();
                    const uint32_t bad = tags_bad<4>(buf, tag, t7);
                    wg_wait<0>();
                    pin(acc);
                    if (wg_all_ok(bad, 3)) break;
                    if (t7 == 0) { mbar_expect_tx(bars + B_UIN + gi * 8, 16384); bulk_ld(buf, g_U + (size_t)(extra ? 0 : bid * 2 + gi) * 16384, 16384, bars + B_UIN + gi * 8); }
                }
                STAMP3(30);
                uint32_t af[32];
#pragma unroll
                for (int b = 0; b < 4; b++)
#pragma unroll
                    for (int c = 0; c < 4; c++) {
                        const int i = 4 * (4 * b + c);
                        cf x0 = cmul({acc[i], acc[i + 2]}, T[2 * c]), x1 = cmul({acc[i + 1], acc[i + 3]}, T[2 * c + 1]);
                        af[16 * (b >> 1) + 4 * c + (b & 1)] = pk(x0.x, x0.y);
                        af[16 * (b >> 1) + 4 * c + 2 + (b & 1)] = pk(x1.x, x1.y);
                    }
                pinu(af);
                wg_fence();
#pragma unroll
                for (int j = 0; j < 4; j++) {
                    const uint64_t db = dF + j * 2;
                    mma64_rs<0>(za, af[4 * j], af[4 * j + 1], af[4 * j + 2], af[4 * j + 3], db, j);
                    mma64_rs<0>(zb, af[16 + 4 * j], af[17 + 4 * j], af[18 + 4 * j], af[19 + 4 * j], db, j);
                }
                wg_commit();
                STAMP3(31);
                mbar_wait(bars + B_WD, gi);
                cf W0[8];
#pragma unroll
                for (int i = 0; i < 8; i++) W0[i] = {lds_bf(wad[i & 3] + 64 * (i >> 2)), lds_bf(wad[i & 3] + 64 * (i >> 2) + 4 * WPITCH)};
                wg_wait<0>();
                pin(za);
                pin(zb);
                pinu(af);
                STAMP3(32);
#pragma unroll
                for (int jb = 0; jb < 4; jb++) {
                    if (jb == 2) {
                        STAMP3(37);
                        mbar_wait(bars + B_WM, gi);
#pragma unroll
                        for (int j = 0; j < 4; j++)
                            wad[j] = sb + OFF_P + (gi ^ 1) * 16384 + (((kap ? 3 : 4) - j - q) & 3) * WPITCH + ((-2 * kap) & 15) + 1024 - 2 * k1 - 128 * q;
                    }
                    if (jb == 3) load_T(T, t7);
                    cf z[2][4];
#pragma unroll
                    for (int e = 0; e < 2; e++) {
                        cf W[4];
#pragma unroll
                        for (int j = 0; j < 4; j++) {
                            const int off = jb < 2 ? 512 * jb + 64 * e : -(512 * (jb - 2) + 64 * e);
                            if (jb == 0) W[j] = W0[4 * e + j];
                            else W[j] = {lds_bf(wad[j] + off), lds_bf(wad[j] + off + 4 * WPITCH)};
                            if (jb >= 2) W[j].y = -W[j].y;
                        }
                        if ((jb & 1) == 0 && e == 0 && t7 == 0) {
                            lds128f(sb + OFF_WSP + gi * 64 + jb * 16, W[0].x, W[0].y, W[1].x, W[1].y);
                            lds128f(sb + OFF_WSP + gi * 64 + jb * 16 + 16, W[2].x, W[2].y, W[3].x, W[3].y);
                        }
                        const int i = 8 * jb + e;
                        const cf z0 = {za[i], za[i + 4]}, z1 = cmul({za[i + 2], za[i + 6]}, be1);
                        cf s0 = cfma({zb[i], zb[i + 4]}, be2, z0), s1 = twice_minus(z0, s0);
                        cf s2 = cfma({zb[i + 2], zb[i + 6]}, be3, z1), s3 = twice_minus(z1, s2);
                        const cf y0 = cmul(cadd(s0, s2), W[0]), y1 = cmul({s1.x + s3.y, s1.y - s3.x}, W[1]);
                        const cf x2 = csub(s0, s2), x3 = {s1.x - s3.y, s1.y + s3.x};
                        s0 = cfma(x2, W[2], y0); s1 = twice_minus(y0, s0);
                        s2 = cfma(x3, W[3], y1); s3 = twice_minus(y1, s2);
                        z[e][0] = cadd(s0, s2);
                        z[e][2] = cmulc(csub(s0, s2), be2);
                        z[e][1] = cmulc({s1.x - s3.y, s1.y + s3.x}, be1);
                        z[e][3] = cmulc({s1.x + s3.y, s1.y - s3.x}, be3);
                    }
#pragma unroll
                    for (int b = 0; b < 4; b++) {
                        af[16 * (b >> 1) + 4 * jb + (b & 1)] = pk(z[0][b].x, z[1][b].x);
                        af[16 * (b >> 1) + 4 * jb + 2 + (b & 1)] = pk(z[0][b].y, z[1][b].y);
                    }
                }
                pinu(af);
                __syncwarp();
                if (lane == 0) mbar_arrive(bars + B_WFREE);
                wg_fence();
#pragma unroll
                for (int j = 0; j < 4; j++) {
                    const uint64_t db = dF + j * 128;
                    mma64_rs<1>(ya, af[4 * j], af[4 * j + 1], af[4 * j + 2], af[4 * j + 3], db, j);
                    mma64_rs<1>(yb, af[16 + 4 * j], af[17 + 4 * j], af[18 + 4 * j], af[19 + 4 * j], db, j);
                }
                wg_commit();
                STAMP3(33);
                wg_wait<0>();
                STAMP3(34);
                pin(ya);
                pin(yb);
                pinu(af);
                {
                    const uint32_t a0 = buf + (mi & 1) * 4096 + (16 * w + 8 * (mi >> 1) + gl) * 64;
#pragma unroll
                    for (int u = 0; u < 2; u++)
#pragma unroll
                        for (int c = 0; c < 4; c++) {
                            const int i = 8 * c;
                            const float(&yy)[32] = u ? yb : ya;
                            cf x0 = cmulc({yy[i], yy[i + 1]}, T[2 * c]), x1 = cmulc({yy[i + 4], yy[i + 5]}, T[2 * c + 1]);
                            cf y0 = cmulc({yy[i + 2], yy[i + 3]}, T[2 * c]), y1 = cmulc({yy[i + 6], yy[i + 7]}, T[2 * c + 1]);
                            stsm4(a0 + u * 8192 + ((c ^ (gl >> 1)) << 4), pk(x0.x, x1.x), pk(y0.x, y1.x), pk(x0.y, x1.y), pk(y0.y, y1.y));
                        }
                }
                STAMP3(38);
                fence_async_sm();
                bar_sync(3, 128);
                wg_fence();
#pragma unroll
                for (int j = 0; j < 4; j++) mma128_ss<0, 1, 1>(vv, dF + j * 128, dB + j * 64, j);
                wg_commit();
                STAMP3(35);
                int cj = 0, s3 = 0;
                if (!extra) s3 = slot3_of(kap, cj);
                const uint32_t flip = ((g & 1) && !cj) ? 0x80008000u : 0u, flipt = flip | (tag & ~tmask);
                wg_wait<0>();
                pin(vv);
                STAMP3(36);
                bar_sync(3, 128);
                {
                    const int rw = 8 * w + (gl & 6) + (mi & 1);
                    const uint32_t a0 = (extra ? ((gl & 1) == gi ? sb : sb + 16384) : buf) + rw * 64 +
                                        (((((gl & 1) << 1) | ((mi >> 1) ^ ((s3 >> 1) & 1))) ^ ((rw >> 1) & 3)) << 4);
#pragma unroll
                    for (int b = 0; b < 4; b++)
#pragma unroll
                        for (int c = 0; c < 4; c += 2) {
                            const int i = 4 * (4 * b + c);
                            stsm4(a0 + b * 2048 + c * 4096, (pk(vv[i], vv[i + 1]) & tmask) ^ flipt, (pk(vv[i + 2], vv[i + 3]) & tmask) ^ flipt,
                                  pk(vv[i + 4], vv[i + 5]) ^ flip, pk(vv[i + 6], vv[i + 7]) ^ flip);
                        }
                }
                fence_async_sm();
                __syncwarp();
                if (lane == 0) mbar_arrive(bars + B_STG);

            }
        }
        if (extra) return;
        }
        {
            uint32_t sp[8];
#pragma unroll
            for (int j = 0; j < 2; j++) { const uint4 v = ldtab(TAB_SP + j * 512 + t7 * 4); sp[4 * j] = v.x; sp[4 * j + 1] = v.y; sp[4 * j + 2] = v.z; sp[4 * j + 3] = v.w; }
            cf tw[8];
            load_tw(tw, k1);
            tw[4].x *= 2.f; tw[4].y *= 2.f;
            const uint32_t tag = get_epoch(bars) & 1;
            const uint32_t in = sb + OFF_P + hf * 16384;
            const uint64_t dF = opaque(mkdesc(sb + OFF_F, 16, 1024, 1)), dB = opaque(mkdesc(in, 2048, 256, 3));
            float acc[64];
#pragma unroll 1
            for (int n = 0; n < 4096; n++) {
                mbar_wait(bars + B_VIN + hf * 8, n & 1);
                STAMP(25);
                pinu(sp);
                wg_fence();
#pragma unroll
                for (int j = 0; j < 4; j++) {
                    mma112_ss(acc, dF + j * 2, dB + 128 + j * 32, j);
                    if (j < 2) mma16_rs(acc, sp[2 * j], 0u, sp[2 * j + 1], 0u, dB + j * 32, j);
                    else mma16_rs(acc, 0u, sp[2 * j], 0u, sp[2 * j + 1], dB + j * 32, 1);
                }
                wg_commit();
                const uint32_t bad = tags_bad<4>(in, tag, t7);
                wg_wait<0>();
                pin(acc);
                pinu(sp);
                if (wg_all_ok(bad, hf ? 3 : 8)) break;
                if (t7 == 0) { mbar_expect_tx(bars + B_VIN + hf * 8, 16384); bulk_ld(in, g_V + (size_t)bid * 32768 + hf * 16384, 16384, bars + B_VIN + hf * 8); }
            }
            uint32_t o[2][16];
#pragma unroll
            for (int cl = 0; cl < 2; cl++) {
                cf z[2][8];
#pragma unroll
                for (int e = 0; e < 2; e++) {
                    const float b0 = acc[4 * cl + e], b8 = acc[4 * cl + 2 + e];
                    z[e][0] = {b0 + b8, b0 - b8};
                    z[e][4] = cmul({acc[4 * (8 + cl) + e], acc[4 * (8 + cl) + 2 + e]}, tw[4]);
#pragma unroll
                    for (int n = 1; n < 4; n++) {
                        const cf w16 = n == 1 ? cf{0.92387953251128674f, -0.38268343236508977f}
                                              : (n == 2 ? cf{0.70710678118654752f, -0.70710678118654752f} : cf{0.38268343236508977f, -0.92387953251128674f});
                        const cf y = cmul({acc[4 * (2 * n + cl) + e], acc[4 * (2 * n + cl) + 2 + e]}, tw[n]);
                        const cf u = {acc[4 * (2 * (8 - n) + cl) + e], acc[4 * (2 * (8 - n) + cl) + 2 + e]}, t = tw[8 - n];
                        const cf E = {fmaf(u.x, t.x, fmaf(-u.y, t.y, y.x)), fmaf(-u.x, t.y, fmaf(-u.y, t.x, y.y))};
                        const cf D = twice_minus(y, E);
                        z[e][n] = {fmaf(-D.x, w16.y, fmaf(-D.y, w16.x, E.x)), fmaf(D.x, w16.x, fmaf(-D.y, w16.y, E.y))};
                        z[e][8 - n] = {fmaf(2.f, E.x, -z[e][n].x), fmaf(-2.f, E.y, z[e][n].y)};
                    }
                    dft8<false>(z[e], tw);
                }
#pragma unroll
                for (int m = 0; m < 8; m++) { o[cl][2 * m] = pk(z[0][m].x, z[1][m].x); o[cl][2 * m + 1] = pk(z[0][m].y, z[1][m].y); }
            }
            const uint32_t a0 = in + (8 * w + gl + 32 * (mi >> 1)) * 32 + (((mi & 1) ^ (gl >> 2)) << 4);
#pragma unroll
            for (int m = 0; m < 16; m += 2) stsm4(a0 + m * 1024, o[0][m], o[1][m], o[0][m + 1], o[1][m + 1]);
            bar_sync(7, 256);
            STAMP(26);
            const int l8 = lane & 7, n0 = 16 * hf + 4 * w + mi;
            const uint32_t la = sb + OFF_P + (l8 >> 2) * 16384 + n0 * 32 + ((((l8 >> 1) & 1) ^ (w & 1)) << 4) + (l8 & 1) * 8;
            float* op = p.out + (size_t)(4 * n0 + fb) * 2048 + fcb * 32 + l8 * 4;
#pragma unroll 1
            for (int it = 0; it < 16; it += 4) {
                uint32_t u[8], fast;
                asm volatile("{.reg .pred p; mbarrier.test_wait.parity.shared::cta.b64 p, [%1], 0; selp.u32 %0, 1, 0, p;}" : "=r"(fast) : "r"(bars + B_LDONE) : "memory");
#pragma unroll
                for (int i = 0; i < 4; i++) asm volatile("ld.shared.v2.b32 {%0,%1}, [%2];" : "=r"(u[2 * i]), "=r"(u[2 * i + 1]) : "r"(la + (it + i) * 1024) : "memory");
#pragma unroll
                for (int i = 0; i < 4; i++) {
                    asm volatile("st.global.v4.b32 [%0], {%1,%2,%3,%4};" ::"l"(op + (size_t)(it + i) * 128 * 2048), "r"(u[2 * i] << 16), "r"(u[2 * i] & 0xffff0000u), "r"(u[2 * i + 1] << 16), "r"(u[2 * i + 1] & 0xffff0000u) : "memory");
                    if (!fast) __nanosleep(PACE_O);
                }
            }
            STAMP(27);
        }
    }
}

typedef CUresult (*EncodeFn)(CUtensorMap*, CUtensorMapDataType, cuuint32_t, void*, const cuuint64_t*, const cuuint64_t*, const cuuint32_t*,
                             const cuuint32_t*, CUtensorMapInterleave, CUtensorMapSwizzle, CUtensorMapL2promotion, CUtensorMapFloatOOBfill);

static CUtensorMap make_map(EncodeFn enc, const void* ptr, int rank, const cuuint64_t* dims, const cuuint64_t* strides, const cuuint32_t* box,
                            CUtensorMapSwizzle swz, CUtensorMapL2promotion promo, CUtensorMapDataType dt = CU_TENSOR_MAP_DATA_TYPE_BFLOAT16) {
    CUtensorMap m;
    const cuuint32_t es[5] = {1, 1, 1, 1, 1};
    enc(&m, dt, rank, const_cast<void*>(ptr), dims, strides, box, es, CU_TENSOR_MAP_INTERLEAVE_NONE, swz, promo,
        CU_TENSOR_MAP_FLOAT_OOB_FILL_NONE);
    return m;
}

extern "C" void kernel_launch(void* const* d_in, const int* in_sizes, int n_in, void* d_out, int out_size) {
    void* fn = nullptr;
    cudaDriverEntryPointQueryResult qr;
    cudaGetDriverEntryPoint("cuTensorMapEncodeTiled", &fn, cudaEnableDefault, &qr);
    EncodeFn enc = (EncodeFn)fn;
    void *pU, *pV;
    cudaGetSymbolAddress(&pU, g_U);
    cudaGetSymbolAddress(&pV, g_V);
    const CUtensorMapL2promotion P256 = CU_TENSOR_MAP_L2_PROMOTION_L2_256B, P0 = CU_TENSOR_MAP_L2_PROMOTION_NONE;

    const cuuint64_t dX[5] = {1024, 2, 4, 16, 16}, sX[4] = {2048, 32 * 2048, 2 * 2048, 128 * 2048};
    const cuuint32_t bX[5] = {64, 2, 4, 16, 1};
    CUtensorMap tmX = make_map(enc, d_in[3], 5, dX, sX, bX, CU_TENSOR_MAP_SWIZZLE_128B, P256);
    const cuuint64_t dW[2] = {1024, 1024}, sW[1] = {2048};
    const cuuint32_t bB[2] = {64, 64}, bC[2] = {64, 128};
    const cuuint64_t dXd[2] = {1024, 2048};
    CUtensorMap tmXd = make_map(enc, d_in[3], 2, dXd, sW, bC, CU_TENSOR_MAP_SWIZZLE_128B, P256);
    CUtensorMap tmBre = make_map(enc, d_in[6], 2, dW, sW, bB, CU_TENSOR_MAP_SWIZZLE_128B, P256);
    CUtensorMap tmBim = make_map(enc, d_in[7], 2, dW, sW, bB, CU_TENSOR_MAP_SWIZZLE_128B, P256);
    CUtensorMap tmCre = make_map(enc, d_in[8], 2, dW, sW, bB, CU_TENSOR_MAP_SWIZZLE_128B, P256);
    CUtensorMap tmCim = make_map(enc, d_in[9], 2, dW, sW, bB, CU_TENSOR_MAP_SWIZZLE_128B, P256);

    const cuuint64_t dU[2] = {8192, 256}, sU[1] = {16384};
    const cuuint32_t bS[2] = {64, UBOX};
    CUtensorMap tmUst = make_map(enc, pU, 2, dU, sU, bS, CU_TENSOR_MAP_SWIZZLE_128B, P0);
    const cuuint64_t dV[3] = {8192, 128, 2}, sV[2] = {32768, 16384};
    const cuuint32_t bV[3] = {32, VBOX, 1};
    CUtensorMap tmVst = make_map(enc, pV, 3, dV, sV, bV, CU_TENSOR_MAP_SWIZZLE_64B, P0);
    const cuuint64_t dA[4] = {1024, 64, 8, 4}, sA[3] = {32 * 2048, 4 * 2048, 2048};
    const cuuint32_t bA[4] = {16, 64, 2, 1};
    CUtensorMap tmXA = make_map(enc, d_in[0], 4, dA, sA, bA, CU_TENSOR_MAP_SWIZZLE_32B, CU_TENSOR_MAP_L2_PROMOTION_L2_128B);
    const cuuint64_t dF[2] = {512 * 1026 / 8, 4}, sF[1] = {512 * 1026};
    const cuuint32_t bF[2] = {WPITCH / 8, 4};
    CUtensorMap tmWr = make_map(enc, d_in[1], 2, dF, sF, bF, CU_TENSOR_MAP_SWIZZLE_NONE, P0, CU_TENSOR_MAP_DATA_TYPE_UINT64);
    CUtensorMap tmWi = make_map(enc, d_in[2], 2, dF, sF, bF, CU_TENSOR_MAP_SWIZZLE_NONE, P0, CU_TENSOR_MAP_DATA_TYPE_UINT64);

    Params p;
    p.wr = (const __nv_bfloat16*)d_in[1];
    p.wi = (const __nv_bfloat16*)d_in[2];
    p.xb = (const __nv_bfloat16*)d_in[3];
    p.lre = (const __nv_bfloat16*)d_in[4];
    p.lim = (const __nv_bfloat16*)d_in[5];
    p.ldt = (const __nv_bfloat16*)d_in[10];
    p.dsk = (const __nv_bfloat16*)d_in[11];
    p.out = (float*)d_out;
    cudaFuncSetAttribute(fused_kernel, cudaFuncAttributeMaxDynamicSharedMemorySize, SMEM_BYTES);
    fused_kernel<<<130, 512, SMEM_BYTES>>>(tmX, tmBre, tmBim, tmCre, tmCim, tmXd, tmUst, tmVst, tmWr, tmWi, tmXA, p);
}
```

```cpp
#include <cuda_runtime.h>
#include <cuda.h>
#include <cuda_bf16.h>
#include <stdint.h>

#define NST 5
#define OFF_P (NST * 32768)
#define OFF_F (OFF_P + 32768)
#define OFF_X (OFF_F + 8192)
#define OFF_Q (OFF_X + 8448)
#define OFF_BAR (OFF_Q + 16384)
#define OFF_LAM (OFF_BAR + 384)
#define OFF_WSP (OFF_LAM + 2048)
#define SMEM_BYTES (OFF_WSP + 128)
#define WPITCH 1056
#define B_FULL 0
#define B_EMPTY 48
#define B_HL 304
#define B_HR 112
#define B_XD 96
#define B_EP 128
#define B_LAM 136
#define B_STG 144
#define B_LDONE 160
#define B_FG 168
#define B_UIN 176
#define B_STGU 192
#define B_WSP 200
#define B_WFREE 208
#define B_HOWN 216
#define B_WD 248
#define B_WM 256
#define B_XIN 264
#define B_VIN 280
#define B_EPOCH 296

#define PACE_U 20
#define PACE_V 20
#define PACE_O 150
#define LDK 60
#define UBOX 32
#define VBOX 64
#define SKEW 4
#define SPIN_LIMIT (1u << 15)

__device__ __align__(1024) uint8_t g_U[4 << 20];
__device__ __align__(1024) uint8_t g_V[4 << 20];
__device__ __align__(1024) uint8_t g_H[8 << 20];
__device__ __align__(1024) uint4 g_carry[16 * 512];
__device__ __align__(128) unsigned g_cnt[64];
__device__ __align__(128) unsigned g_epoch[129 * 8];

#define STAMP(i) do { } while (0)
#define STAMPR(i) do { } while (0)
#define STAMPW(a, b) do { } while (0)
#define STAMPX(a, b) do { } while (0)
#define STAMP3(i) do { } while (0)

#define TAB_FG 0
#define TAB_F1 2048
#define TAB_T 4096
#define TAB_SP 6144
#define TAB_TW 7168
#define TAB_FX 7680
__device__ __align__(1024) const uint32_t g_tab[7808] = {
0x80003d80,0x80003d80,0x80003d80,0x80003d80,0x80003d80,0x80003d80,0x80003d80,0x80003d80,0x80003d80,0x80003d80,0x80003d80,0x80003d80,0x80003d80,0x80003d80,0x80003d80,0x80003d80,
0x80003d80,0x80003d80,0x80003d80,0x80003d80,0x80003d80,0x80003d80,0x80003d80,0x80003d80,0x80003d80,0x80003d80,0x80003d80,0x80003d80,0x80003d80,0x80003d80,0x80003d80,0x80003d80,
0x3c483d7b,0x3d0e3d55,0x3d553d0e,0x3d7b3c48,0x80003d80,0x3cc43d6d,0x3d353d35,0x3d6d3cc4,0x3d7bbc48,0x3d55bd0e,0x3d0ebd55,0x3c48bd7b,0x3d800000,0x3d6dbcc4,0x3d35bd35,0x3cc4bd6d,
0xbc48bd7b,0xbd0ebd55,0xbd55bd0e,0xbd7bbc48,0x8000bd80,0xbcc4bd6d,0xbd35bd35,0xbd6dbcc4,0xbd7b3c48,0xbd553d0e,0xbd0e3d55,0xbc483d7b,0xbd800000,0xbd6d3cc4,0xbd353d35,0xbcc43d6d,
0x8000bd80,0xbd35bd35,0xbd800000,0xbd353d35,0xbcc4bd6d,0xbd6dbcc4,0xbd6d3cc4,0xbcc43d6d,0x80003d80,0x3d353d35,0x3d800000,0x3d35bd35,0x3cc43d6d,0x3d6d3cc4,0x3d6dbcc4,0x3cc4bd6d,
0x8000bd80,0xbd35bd35,0xbd800000,0xbd353d35,0xbcc4bd6d,0xbd6dbcc4,0xbd6d3cc4,0xbcc43d6d,0x80003d80,0x3d353d35,0x3d800000,0x3d35bd35,0x3cc43d6d,0x3d6d3cc4,0x3d6dbcc4,0x3cc4bd6d,
0xbd553d0e,0x3c483d7b,0x3d7b3c48,0x3d0ebd55,0xbd800000,0xbcc43d6d,0x3d353d35,0x3d6dbcc4,0x3d0e3d55,0x3d7bbc48,0x3c48bd7b,0xbd55bd0e,0x80003d80,0x3d6d3cc4,0x3d35bd35,0xbcc4bd6d,
0x3d55bd0e,0xbc48bd7b,0xbd7bbc48,0xbd0e3d55,0x3d800000,0x3cc4bd6d,0xbd35bd35,0xbd6d3cc4,0xbd0ebd55,0xbd7b3c48,0xbc483d7b,0x3d553d0e,0x8000bd80,0xbd6dbcc4,0xbd353d35,0x3cc43d6d,
0x80003d80,0x3d800000,0x8000bd80,0xbd800000,0x3d353d35,0x3d35bd35,0xbd35bd35,0xbd353d35,0x80003d80,0x3d800000,0x8000bd80,0xbd800000,0x3d353d35,0x3d35bd35,0xbd35bd35,0xbd353d35,
0x80003d80,0x3d800000,0x8000bd80,0xbd800000,0x3d353d35,0x3d35bd35,0xbd35bd35,0xbd353d35,0x80003d80,0x3d800000,0x8000bd80,0xbd800000,0x3d353d35,0x3d35bd35,0xbd35bd35,0xbd353d35,
0xbd55bd0e,0xbc483d7b,0x3d7bbc48,0xbd0ebd55,0x8000bd80,0xbd6d3cc4,0x3d353d35,0x3cc4bd6d,0xbd0e3d55,0x3d7b3c48,0xbc48bd7b,0xbd553d0e,0xbd800000,0x3cc43d6d,0x3d35bd35,0xbd6dbcc4,
0x3d553d0e,0x3c48bd7b,0xbd7b3c48,0x3d0e3d55,0x80003d80,0x3d6dbcc4,0xbd35bd35,0xbcc43d6d,0x3d0ebd55,0xbd7bbc48,0x3c483d7b,0x3d55bd0e,0x3d800000,0xbcc4bd6d,0xbd353d35,0x3d6d3cc4,
0x8000bd80,0xbd353d35,0x3d800000,0xbd35bd35,0xbd6dbcc4,0x3cc43d6d,0x3cc4bd6d,0xbd6d3cc4,0x80003d80,0x3d35bd35,0xbd800000,0x3d353d35,0x3d6d3cc4,0xbcc4bd6d,0xbcc43d6d,0x3d6dbcc4,
0x8000bd80,0xbd353d35,0x3d800000,0xbd35bd35,0xbd6dbcc4,0x3cc43d6d,0x3cc4bd6d,0xbd6d3cc4,0x80003d80,0x3d35bd35,0xbd800000,0x3d353d35,0x3d6d3cc4,0xbcc4bd6d,0xbcc43d6d,0x3d6dbcc4,
0x3c48bd7b,0xbd0e3d55,0x3d55bd0e,0xbd7b3c48,0x3d800000,0xbd6dbcc4,0x3d353d35,0xbcc4bd6d,0xbd7bbc48,0x3d553d0e,0xbd0ebd55,0x3c483d7b,0x8000bd80,0xbcc43d6d,0x3d35bd35,0xbd6d3cc4,
0xbc483d7b,0x3d0ebd55,0xbd553d0e,0x3d7bbc48,0xbd800000,0x3d6d3cc4,0xbd35bd35,0x3cc43d6d,0x3d7b3c48,0xbd55bd0e,0x3d0e3d55,0xbc48bd7b,0x80003d80,0x3cc4bd6d,0xbd353d35,0x3d6dbcc4,
0x3d800000,0x3d800000,0x3d800000,0x3d800000,0x3d800000,0x3d800000,0x3d800000,0x3d800000,0x3d800000,0x3d800000,0x3d800000,0x3d800000,0x3d800000,0x3d800000,0x3d800000,0x3d800000,
0x3d800000,0x3d800000,0x3d800000,0x3d800000,0x3d800000,0x3d800000,0x3d800000,0x3d800000,0x3d800000,0x3d800000,0x3d800000,0x3d800000,0x3d800000,0x3d800000,0x3d800000,0x3d800000,
0x3d7bbc48,0x3d55bd0e,0x3d0ebd55,0x3c48bd7b,0x3d800000,0x3d6dbcc4,0x3d35bd35,0x3cc4bd6d,0xbc48bd7b,0xbd0ebd55,0xbd55bd0e,0xbd7bbc48,0xbd80,0xbcc4bd6d,0xbd35bd35,0xbd6dbcc4,
0xbd7b3c48,0xbd553d0e,0xbd0e3d55,0xbc483d7b,0xbd800000,0xbd6d3cc4,0xbd353d35,0xbcc43d6d,0x3c483d7b,0x3d0e3d55,0x3d553d0e,0x3d7b3c48,0x3d80,0x3cc43d6d,0x3d353d35,0x3d6d3cc4,
0xbd800000,0xbd353d35,0x3d80,0x3d353d35,0xbd6d3cc4,0xbcc43d6d,0x3cc43d6d,0x3d6d3cc4,0x3d800000,0x3d35bd35,0xbd80,0xbd35bd35,0x3d6dbcc4,0x3cc4bd6d,0xbcc4bd6d,0xbd6dbcc4,
0xbd800000,0xbd353d35,0x3d80,0x3d353d35,0xbd6d3cc4,0xbcc43d6d,0x3cc43d6d,0x3d6d3cc4,0x3d800000,0x3d35bd35,0xbd80,0xbd35bd35,0x3d6dbcc4,0x3cc4bd6d,0xbcc4bd6d,0xbd6dbcc4,
0x3d0e3d55,0x3d7bbc48,0x3c48bd7b,0xbd55bd0e,0x3d80,0x3d6d3cc4,0x3d35bd35,0xbcc4bd6d,0x3d55bd0e,0xbc48bd7b,0xbd7bbc48,0xbd0e3d55,0x3d800000,0x3cc4bd6d,0xbd35bd35,0xbd6d3cc4,
0xbd0ebd55,0xbd7b3c48,0xbc483d7b,0x3d553d0e,0xbd80,0xbd6dbcc4,0xbd353d35,0x3cc43d6d,0xbd553d0e,0x3c483d7b,0x3d7b3c48,0x3d0ebd55,0xbd800000,0xbcc43d6d,0x3d353d35,0x3d6dbcc4,
0x3d800000,0xbd80,0xbd800000,0x3d80,0x3d35bd35,0xbd35bd35,0xbd353d35,0x3d353d35,0x3d800000,0xbd80,0xbd800000,0x3d80,0x3d35bd35,0xbd35bd35,0xbd353d35,0x3d353d35,
0x3d800000,0xbd80,0xbd800000,0x3d80,0x3d35bd35,0xbd35bd35,0xbd353d35,0x3d353d35,0x3d800000,0xbd80,0xbd800000,0x3d80,0x3d35bd35,0xbd35bd35,0xbd353d35,0x3d353d35,
0xbd0e3d55,0x3d7b3c48,0xbc48bd7b,0xbd553d0e,0xbd800000,0x3cc43d6d,0x3d35bd35,0xbd6dbcc4,0x3d553d0e,0x3c48bd7b,0xbd7b3c48,0x3d0e3d55,0x3d80,0x3d6dbcc4,0xbd35bd35,0xbcc43d6d,
0x3d0ebd55,0xbd7bbc48,0x3c483d7b,0x3d55bd0e,0x3d800000,0xbcc4bd6d,0xbd353d35,0x3d6d3cc4,0xbd55bd0e,0xbc483d7b,0x3d7bbc48,0xbd0ebd55,0xbd80,0xbd6d3cc4,0x3d353d35,0x3cc4bd6d,
0xbd800000,0x3d353d35,0xbd80,0xbd353d35,0xbcc43d6d,0x3d6dbcc4,0xbd6dbcc4,0x3cc43d6d,0x3d800000,0xbd35bd35,0x3d80,0x3d35bd35,0x3cc4bd6d,0xbd6d3cc4,0x3d6d3cc4,0xbcc4bd6d,
0xbd800000,0x3d353d35,0xbd80,0xbd353d35,0xbcc43d6d,0x3d6dbcc4,0xbd6dbcc4,0x3cc43d6d,0x3d800000,0xbd35bd35,0x3d80,0x3d35bd35,0x3cc4bd6d,0xbd6d3cc4,0x3d6d3cc4,0xbcc4bd6d,
0xbd7bbc48,0x3d553d0e,0xbd0ebd55,0x3c483d7b,0xbd80,0xbcc43d6d,0x3d35bd35,0xbd6d3cc4,0xbc483d7b,0x3d0ebd55,0xbd553d0e,0x3d7bbc48,0xbd800000,0x3d6d3cc4,0xbd35bd35,0x3cc43d6d,
0x3d7b3c48,0xbd55bd0e,0x3d0e3d55,0xbc48bd7b,0x3d80,0x3cc4bd6d,0xbd353d35,0x3d6dbcc4,0x3c48bd7b,0xbd0e3d55,0x3d55bd0e,0xbd7b3c48,0x3d800000,0xbd6dbcc4,0x3d353d35,0xbcc4bd6d,
0x80003d80,0x8000bd80,0x80003d80,0x8000bd80,0x3d800000,0xbd800000,0x3d800000,0xbd800000,0x80003d80,0x8000bd80,0x80003d80,0x8000bd80,0x3d800000,0xbd800000,0x3d800000,0xbd800000,
0x80003d80,0x8000bd80,0x80003d80,0x8000bd80,0x3d800000,0xbd800000,0x3d800000,0xbd800000,0x80003d80,0x8000bd80,0x80003d80,0x8000bd80,0x3d800000,0xbd800000,0x3d800000,0xbd800000,
0x3d7bbc48,0xbd553d0e,0x3d0ebd55,0xbc483d7b,0x80003d80,0xbcc4bd6d,0x3d353d35,0xbd6dbcc4,0xbc48bd7b,0x3d0e3d55,0xbd55bd0e,0x3d7b3c48,0x3d800000,0xbd6d3cc4,0x3d35bd35,0xbcc43d6d,
0xbd7b3c48,0x3d55bd0e,0xbd0e3d55,0x3c48bd7b,0x8000bd80,0x3cc43d6d,0xbd35bd35,0x3d6d3cc4,0x3c483d7b,0xbd0ebd55,0x3d553d0e,0xbd7bbc48,0xbd800000,0x3d6dbcc4,0xbd353d35,0x3cc4bd6d,
0x8000bd80,0x3d353d35,0xbd800000,0x3d35bd35,0xbd6d3cc4,0x3cc4bd6d,0x3cc43d6d,0xbd6dbcc4,0x80003d80,0xbd35bd35,0x3d800000,0xbd353d35,0x3d6dbcc4,0xbcc43d6d,0xbcc4bd6d,0x3d6d3cc4,
0x8000bd80,0x3d353d35,0xbd800000,0x3d35bd35,0xbd6d3cc4,0x3cc4bd6d,0x3cc43d6d,0xbd6dbcc4,0x80003d80,0xbd35bd35,0x3d800000,0xbd353d35,0x3d6dbcc4,0xbcc43d6d,0xbcc4bd6d,0x3d6d3cc4,
0x3d0e3d55,0xbd7b3c48,0x3c48bd7b,0x3d553d0e,0xbd800000,0x3cc4bd6d,0x3d353d35,0xbd6d3cc4,0x3d55bd0e,0x3c483d7b,0xbd7bbc48,0x3d0ebd55,0x80003d80,0xbd6dbcc4,0x3d35bd35,0x3cc43d6d,
0xbd0ebd55,0x3d7bbc48,0xbc483d7b,0xbd55bd0e,0x3d800000,0xbcc43d6d,0xbd35bd35,0x3d6dbcc4,0xbd553d0e,0xbc48bd7b,0x3d7b3c48,0xbd0e3d55,0x8000bd80,0x3d6d3cc4,0xbd353d35,0xbcc4bd6d,
0x80003d80,0xbd800000,0x8000bd80,0x3d800000,0x3d35bd35,0x3d353d35,0xbd353d35,0xbd35bd35,0x80003d80,0xbd800000,0x8000bd80,0x3d800000,0x3d35bd35,0x3d353d35,0xbd353d35,0xbd35bd35,
0x80003d80,0xbd800000,0x8000bd80,0x3d800000,0x3d35bd35,0x3d353d35,0xbd353d35,0xbd35bd35,0x80003d80,0xbd800000,0x8000bd80,0x3d800000,0x3d35bd35,0x3d353d35,0xbd353d35,0xbd35bd35,
0xbd0e3d55,0xbd7bbc48,0xbc48bd7b,0x3d55bd0e,0x8000bd80,0x3d6dbcc4,0x3d353d35,0xbcc43d6d,0x3d553d0e,0xbc483d7b,0xbd7b3c48,0xbd0ebd55,0xbd800000,0xbcc4bd6d,0x3d35bd35,0x3d6d3cc4,
0x3d0ebd55,0x3d7b3c48,0x3c483d7b,0xbd553d0e,0x80003d80,0xbd6d3cc4,0xbd35bd35,0x3cc4bd6d,0xbd55bd0e,0x3c48bd7b,0x3d7bbc48,0x3d0e3d55,0x3d800000,0x3cc43d6d,0xbd353d35,0xbd6dbcc4,
0x8000bd80,0x3d35bd35,0x3d800000,0x3d353d35,0xbcc43d6d,0xbd6d3cc4,0xbd6dbcc4,0xbcc4bd6d,0x80003d80,0xbd353d35,0xbd800000,0xbd35bd35,0x3cc4bd6d,0x3d6dbcc4,0x3d6d3cc4,0x3cc43d6d,
0x8000bd80,0x3d35bd35,0x3d800000,0x3d353d35,0xbcc43d6d,0xbd6d3cc4,0xbd6dbcc4,0xbcc4bd6d,0x80003d80,0xbd353d35,0xbd800000,0xbd35bd35,0x3cc4bd6d,0x3d6dbcc4,0x3d6d3cc4,0x3cc43d6d,
0xbd7bbc48,0xbd55bd0e,0xbd0ebd55,0xbc48bd7b,0x3d800000,0x3d6d3cc4,0x3d353d35,0x3cc43d6d,0xbc483d7b,0xbd0e3d55,0xbd553d0e,0xbd7b3c48,0x8000bd80,0x3cc4bd6d,0x3d35bd35,0x3d6dbcc4,
0x3d7b3c48,0x3d553d0e,0x3d0e3d55,0x3c483d7b,0xbd800000,0xbd6dbcc4,0xbd35bd35,0xbcc4bd6d,0x3c48bd7b,0x3d0ebd55,0x3d55bd0e,0x3d7bbc48,0x80003d80,0xbcc43d6d,0xbd353d35,0xbd6d3cc4,
0x3d800000,0xbd800000,0x3d800000,0xbd800000,0xbd80,0x3d80,0xbd80,0x3d80,0x3d800000,0xbd800000,0x3d800000,0xbd800000,0xbd80,0x3d80,0xbd80,0x3d80,
0x3d800000,0xbd800000,0x3d800000,0xbd800000,0xbd80,0x3d80,0xbd80,0x3d80,0x3d800000,0xbd800000,0x3d800000,0xbd800000,0xbd80,0x3d80,0xbd80,0x3d80,
0xbc48bd7b,0x3d0e3d55,0xbd55bd0e,0x3d7b3c48,0x3d800000,0xbd6d3cc4,0x3d35bd35,0xbcc43d6d,0xbd7b3c48,0x3d55bd0e,0xbd0e3d55,0x3c48bd7b,0xbd80,0x3cc43d6d,0xbd35bd35,0x3d6d3cc4,
0x3c483d7b,0xbd0ebd55,0x3d553d0e,0xbd7bbc48,0xbd800000,0x3d6dbcc4,0xbd353d35,0x3cc4bd6d,0x3d7bbc48,0xbd553d0e,0x3d0ebd55,0xbc483d7b,0x3d80,0xbcc4bd6d,0x3d353d35,0xbd6dbcc4,
0xbd800000,0x3d35bd35,0x3d80,0xbd35bd35,0x3cc43d6d,0xbd6dbcc4,0x3d6dbcc4,0xbcc43d6d,0x3d800000,0xbd353d35,0xbd80,0x3d353d35,0xbcc4bd6d,0x3d6d3cc4,0xbd6d3cc4,0x3cc4bd6d,
0xbd800000,0x3d35bd35,0x3d80,0xbd35bd35,0x3cc43d6d,0xbd6dbcc4,0x3d6dbcc4,0xbcc43d6d,0x3d800000,0xbd353d35,0xbd80,0x3d353d35,0xbcc4bd6d,0x3d6d3cc4,0xbd6d3cc4,0x3cc4bd6d,
0x3d55bd0e,0x3c483d7b,0xbd7bbc48,0x3d0ebd55,0x3d80,0xbd6dbcc4,0x3d35bd35,0x3cc43d6d,0xbd0ebd55,0x3d7bbc48,0xbc483d7b,0xbd55bd0e,0x3d800000,0xbcc43d6d,0xbd35bd35,0x3d6dbcc4,
0xbd553d0e,0xbc48bd7b,0x3d7b3c48,0xbd0e3d55,0xbd80,0x3d6d3cc4,0xbd353d35,0xbcc4bd6d,0x3d0e3d55,0xbd7b3c48,0x3c48bd7b,0x3d553d0e,0xbd800000,0x3cc4bd6d,0x3d353d35,0xbd6d3cc4,
0x3d800000,0x3d80,0xbd800000,0xbd80,0xbd35bd35,0x3d35bd35,0x3d353d35,0xbd353d35,0x3d800000,0x3d80,0xbd800000,0xbd80,0xbd35bd35,0x3d35bd35,0x3d353d35,0xbd353d35,
0x3d800000,0x3d80,0xbd800000,0xbd80,0xbd35bd35,0x3d35bd35,0x3d353d35,0xbd353d35,0x3d800000,0x3d80,0xbd800000,0xbd80,0xbd35bd35,0x3d35bd35,0x3d353d35,0xbd353d35,
0x3d553d0e,0xbc483d7b,0xbd7b3c48,0xbd0ebd55,0xbd800000,0xbcc4bd6d,0x3d35bd35,0x3d6d3cc4,0x3d0ebd55,0x3d7b3c48,0x3c483d7b,0xbd553d0e,0x3d80,0xbd6d3cc4,0xbd35bd35,0x3cc4bd6d,
0xbd55bd0e,0x3c48bd7b,0x3d7bbc48,0x3d0e3d55,0x3d800000,0x3cc43d6d,0xbd353d35,0xbd6dbcc4,0xbd0e3d55,0xbd7bbc48,0xbc48bd7b,0x3d55bd0e,0xbd80,0x3d6dbcc4,0x3d353d35,0xbcc43d6d,
0xbd800000,0xbd35bd35,0xbd80,0x3d35bd35,0x3d6d3cc4,0x3cc43d6d,0xbcc43d6d,0xbd6d3cc4,0x3d800000,0x3d353d35,0x3d80,0xbd353d35,0xbd6dbcc4,0xbcc4bd6d,0x3cc4bd6d,0x3d6dbcc4,
0xbd800000,0xbd35bd35,0xbd80,0x3d35bd35,0x3d6d3cc4,0x3cc43d6d,0xbcc43d6d,0xbd6d3cc4,0x3d800000,0x3d353d35,0x3d80,0xbd353d35,0xbd6dbcc4,0xbcc4bd6d,0x3cc4bd6d,0x3d6dbcc4,
0xbc483d7b,0xbd0e3d55,0xbd553d0e,0xbd7b3c48,0xbd80,0x3cc4bd6d,0x3d35bd35,0x3d6dbcc4,0x3d7b3c48,0x3d553d0e,0x3d0e3d55,0x3c483d7b,0xbd800000,0xbd6dbcc4,0xbd35bd35,0xbcc4bd6d,
0x3c48bd7b,0x3d0ebd55,0x3d55bd0e,0x3d7bbc48,0x3d80,0xbcc43d6d,0xbd353d35,0xbd6d3cc4,0xbd7bbc48,0xbd55bd0e,0xbd0ebd55,0xbc48bd7b,0x3d800000,0x3d6d3cc4,0x3d353d35,0x3cc43d6d,
0x80003d80,0x80003d80,0x80003d80,0x80003d80,0x8000bd80,0x8000bd80,0x8000bd80,0x8000bd80,0x80003d80,0x80003d80,0x80003d80,0x80003d80,0x8000bd80,0x8000bd80,0x8000bd80,0x8000bd80,
0x80003d80,0x80003d80,0x80003d80,0x80003d80,0x8000bd80,0x8000bd80,0x8000bd80,0x8000bd80,0x80003d80,0x80003d80,0x80003d80,0x80003d80,0x8000bd80,0x8000bd80,0x8000bd80,0x8000bd80,
0xbc48bd7b,0xbd0ebd55,0xbd55bd0e,0xbd7bbc48,0x80003d80,0x3cc43d6d,0x3d353d35,0x3d6d3cc4,0xbd7b3c48,0xbd553d0e,0xbd0e3d55,0xbc483d7b,0x3d800000,0x3d6dbcc4,0x3d35bd35,0x3cc4bd6d,
0x3c483d7b,0x3d0e3d55,0x3d553d0e,0x3d7b3c48,0x8000bd80,0xbcc4bd6d,0xbd35bd35,0xbd6dbcc4,0x3d7bbc48,0x3d55bd0e,0x3d0ebd55,0x3c48bd7b,0xbd800000,0xbd6d3cc4,0xbd353d35,0xbcc43d6d,
0x8000bd80,0xbd35bd35,0xbd800000,0xbd353d35,0x3cc43d6d,0x3d6d3cc4,0x3d6dbcc4,0x3cc4bd6d,0x80003d80,0x3d353d35,0x3d800000,0x3d35bd35,0xbcc4bd6d,0xbd6dbcc4,0xbd6d3cc4,0xbcc43d6d,
0x8000bd80,0xbd35bd35,0xbd800000,0xbd353d35,0x3cc43d6d,0x3d6d3cc4,0x3d6dbcc4,0x3cc4bd6d,0x80003d80,0x3d353d35,0x3d800000,0x3d35bd35,0xbcc4bd6d,0xbd6dbcc4,0xbd6d3cc4,0xbcc43d6d,
0x3d55bd0e,0xbc48bd7b,0xbd7bbc48,0xbd0e3d55,0xbd800000,0xbcc43d6d,0x3d353d35,0x3d6dbcc4,0xbd0ebd55,0xbd7b3c48,0xbc483d7b,0x3d553d0e,0x80003d80,0x3d6d3cc4,0x3d35bd35,0xbcc4bd6d,
0xbd553d0e,0x3c483d7b,0x3d7b3c48,0x3d0ebd55,0x3d800000,0x3cc4bd6d,0xbd35bd35,0xbd6d3cc4,0x3d0e3d55,0x3d7bbc48,0x3c48bd7b,0xbd55bd0e,0x8000bd80,0xbd6dbcc4,0xbd353d35,0x3cc43d6d,
0x80003d80,0x3d800000,0x8000bd80,0xbd800000,0xbd35bd35,0xbd353d35,0x3d353d35,0x3d35bd35,0x80003d80,0x3d800000,0x8000bd80,0xbd800000,0xbd35bd35,0xbd353d35,0x3d353d35,0x3d35bd35,
0x80003d80,0x3d800000,0x8000bd80,0xbd800000,0xbd35bd35,0xbd353d35,0x3d353d35,0x3d35bd35,0x80003d80,0x3d800000,0x8000bd80,0xbd800000,0xbd35bd35,0xbd353d35,0x3d353d35,0x3d35bd35,
0x3d553d0e,0x3c48bd7b,0xbd7b3c48,0x3d0e3d55,0x8000bd80,0xbd6d3cc4,0x3d353d35,0x3cc4bd6d,0x3d0ebd55,0xbd7bbc48,0x3c483d7b,0x3d55bd0e,0xbd800000,0x3cc43d6d,0x3d35bd35,0xbd6dbcc4,
0xbd55bd0e,0xbc483d7b,0x3d7bbc48,0xbd0ebd55,0x80003d80,0x3d6dbcc4,0xbd35bd35,0xbcc43d6d,0xbd0e3d55,0x3d7b3c48,0xbc48bd7b,0xbd553d0e,0x3d800000,0xbcc4bd6d,0xbd353d35,0x3d6d3cc4,
0x8000bd80,0xbd353d35,0x3d800000,0xbd35bd35,0x3d6d3cc4,0xbcc4bd6d,0xbcc43d6d,0x3d6dbcc4,0x80003d80,0x3d35bd35,0xbd800000,0x3d353d35,0xbd6dbcc4,0x3cc43d6d,0x3cc4bd6d,0xbd6d3cc4,
0x8000bd80,0xbd353d35,0x3d800000,0xbd35bd35,0x3d6d3cc4,0xbcc4bd6d,0xbcc43d6d,0x3d6dbcc4,0x80003d80,0x3d35bd35,0xbd800000,0x3d353d35,0xbd6dbcc4,0x3cc43d6d,0x3cc4bd6d,0xbd6d3cc4,
0xbc483d7b,0x3d0ebd55,0xbd553d0e,0x3d7bbc48,0x3d800000,0xbd6dbcc4,0x3d353d35,0xbcc4bd6d,0x3d7b3c48,0xbd55bd0e,0x3d0e3d55,0xbc48bd7b,0x8000bd80,0xbcc43d6d,0x3d35bd35,0xbd6d3cc4,
0x3c48bd7b,0xbd0e3d55,0x3d55bd0e,0xbd7b3c48,0xbd800000,0x3d6d3cc4,0xbd35bd35,0x3cc43d6d,0xbd7bbc48,0x3d553d0e,0xbd0ebd55,0x3c483d7b,0x80003d80,0x3cc4bd6d,0xbd353d35,0x3d6dbcc4,
0x3d800000,0x3d800000,0x3d800000,0x3d800000,0xbd800000,0xbd800000,0xbd800000,0xbd800000,0x3d800000,0x3d800000,0x3d800000,0x3d800000,0xbd800000,0xbd800000,0xbd800000,0xbd800000,
0x3d800000,0x3d800000,0x3d800000,0x3d800000,0xbd800000,0xbd800000,0xbd800000,0xbd800000,0x3d800000,0x3d800000,0x3d800000,0x3d800000,0xbd800000,0xbd800000,0xbd800000,0xbd800000,
0xbd7b3c48,0xbd553d0e,0xbd0e3d55,0xbc483d7b,0x3d800000,0x3d6dbcc4,0x3d35bd35,0x3cc4bd6d,0x3c483d7b,0x3d0e3d55,0x3d553d0e,0x3d7b3c48,0xbd80,0xbcc4bd6d,0xbd35bd35,0xbd6dbcc4,
0x3d7bbc48,0x3d55bd0e,0x3d0ebd55,0x3c48bd7b,0xbd800000,0xbd6d3cc4,0xbd353d35,0xbcc43d6d,0xbc48bd7b,0xbd0ebd55,0xbd55bd0e,0xbd7bbc48,0x3d80,0x3cc43d6d,0x3d353d35,0x3d6d3cc4,
0xbd800000,0xbd353d35,0x3d80,0x3d353d35,0x3d6dbcc4,0x3cc4bd6d,0xbcc4bd6d,0xbd6dbcc4,0x3d800000,0x3d35bd35,0xbd80,0xbd35bd35,0xbd6d3cc4,0xbcc43d6d,0x3cc43d6d,0x3d6d3cc4,
0xbd800000,0xbd353d35,0x3d80,0x3d353d35,0x3d6dbcc4,0x3cc4bd6d,0xbcc4bd6d,0xbd6dbcc4,0x3d800000,0x3d35bd35,0xbd80,0xbd35bd35,0xbd6d3cc4,0xbcc43d6d,0x3cc43d6d,0x3d6d3cc4,
0xbd0ebd55,0xbd7b3c48,0xbc483d7b,0x3d553d0e,0x3d80,0x3d6d3cc4,0x3d35bd35,0xbcc4bd6d,0xbd553d0e,0x3c483d7b,0x3d7b3c48,0x3d0ebd55,0x3d800000,0x3cc4bd6d,0xbd35bd35,0xbd6d3cc4,
0x3d0e3d55,0x3d7bbc48,0x3c48bd7b,0xbd55bd0e,0xbd80,0xbd6dbcc4,0xbd353d35,0x3cc43d6d,0x3d55bd0e,0xbc48bd7b,0xbd7bbc48,0xbd0e3d55,0xbd800000,0xbcc43d6d,0x3d353d35,0x3d6dbcc4,
0x3d800000,0xbd80,0xbd800000,0x3d80,0xbd353d35,0x3d353d35,0x3d35bd35,0xbd35bd35,0x3d800000,0xbd80,0xbd800000,0x3d80,0xbd353d35,0x3d353d35,0x3d35bd35,0xbd35bd35,
0x3d800000,0xbd80,0xbd800000,0x3d80,0xbd353d35,0x3d353d35,0x3d35bd35,0xbd35bd35,0x3d800000,0xbd80,0xbd800000,0x3d80,0xbd353d35,0x3d353d35,0x3d35bd35,0xbd35bd35,
0x3d0ebd55,0xbd7bbc48,0x3c483d7b,0x3d55bd0e,0xbd800000,0x3cc43d6d,0x3d35bd35,0xbd6dbcc4,0xbd55bd0e,0xbc483d7b,0x3d7bbc48,0xbd0ebd55,0x3d80,0x3d6dbcc4,0xbd35bd35,0xbcc43d6d,
0xbd0e3d55,0x3d7b3c48,0xbc48bd7b,0xbd553d0e,0x3d800000,0xbcc4bd6d,0xbd353d35,0x3d6d3cc4,0x3d553d0e,0x3c48bd7b,0xbd7b3c48,0x3d0e3d55,0xbd80,0xbd6d3cc4,0x3d353d35,0x3cc4bd6d,
0xbd800000,0x3d353d35,0xbd80,0xbd353d35,0x3cc4bd6d,0xbd6d3cc4,0x3d6d3cc4,0xbcc4bd6d,0x3d800000,0xbd35bd35,0x3d80,0x3d35bd35,0xbcc43d6d,0x3d6dbcc4,0xbd6dbcc4,0x3cc43d6d,
0xbd800000,0x3d353d35,0xbd80,0xbd353d35,0x3cc4bd6d,0xbd6d3cc4,0x3d6d3cc4,0xbcc4bd6d,0x3d800000,0xbd35bd35,0x3d80,0x3d35bd35,0xbcc43d6d,0x3d6dbcc4,0xbd6dbcc4,0x3cc43d6d,
0x3d7b3c48,0xbd55bd0e,0x3d0e3d55,0xbc48bd7b,0xbd80,0xbcc43d6d,0x3d35bd35,0xbd6d3cc4,0x3c48bd7b,0xbd0e3d55,0x3d55bd0e,0xbd7b3c48,0xbd800000,0x3d6d3cc4,0xbd35bd35,0x3cc43d6d,
0xbd7bbc48,0x3d553d0e,0xbd0ebd55,0x3c483d7b,0x3d80,0x3cc4bd6d,0xbd353d35,0x3d6dbcc4,0xbc483d7b,0x3d0ebd55,0xbd553d0e,0x3d7bbc48,0x3d800000,0xbd6dbcc4,0x3d353d35,0xbcc4bd6d,
0x80003d80,0x8000bd80,0x80003d80,0x8000bd80,0xbd800000,0x3d800000,0xbd800000,0x3d800000,0x80003d80,0x8000bd80,0x80003d80,0x8000bd80,0xbd800000,0x3d800000,0xbd800000,0x3d800000,
0x80003d80,0x8000bd80,0x80003d80,0x8000bd80,0xbd800000,0x3d800000,0xbd800000,0x3d800000,0x80003d80,0x8000bd80,0x80003d80,0x8000bd80,0xbd800000,0x3d800000,0xbd800000,0x3d800000,
0xbd7b3c48,0x3d55bd0e,0xbd0e3d55,0x3c48bd7b,0x80003d80,0xbcc4bd6d,0x3d353d35,0xbd6dbcc4,0x3c483d7b,0xbd0ebd55,0x3d553d0e,0xbd7bbc48,0x3d800000,0xbd6d3cc4,0x3d35bd35,0xbcc43d6d,
0x3d7bbc48,0xbd553d0e,0x3d0ebd55,0xbc483d7b,0x8000bd80,0x3cc43d6d,0xbd35bd35,0x3d6d3cc4,0xbc48bd7b,0x3d0e3d55,0xbd55bd0e,0x3d7b3c48,0xbd800000,0x3d6dbcc4,0xbd353d35,0x3cc4bd6d,
0x8000bd80,0x3d353d35,0xbd800000,0x3d35bd35,0x3d6dbcc4,0xbcc43d6d,0xbcc4bd6d,0x3d6d3cc4,0x80003d80,0xbd35bd35,0x3d800000,0xbd353d35,0xbd6d3cc4,0x3cc4bd6d,0x3cc43d6d,0xbd6dbcc4,
0x8000bd80,0x3d353d35,0xbd800000,0x3d35bd35,0x3d6dbcc4,0xbcc43d6d,0xbcc4bd6d,0x3d6d3cc4,0x80003d80,0xbd35bd35,0x3d800000,0xbd353d35,0xbd6d3cc4,0x3cc4bd6d,0x3cc43d6d,0xbd6dbcc4,
0xbd0ebd55,0x3d7bbc48,0xbc483d7b,0xbd55bd0e,0xbd800000,0x3cc4bd6d,0x3d353d35,0xbd6d3cc4,0xbd553d0e,0xbc48bd7b,0x3d7b3c48,0xbd0e3d55,0x80003d80,0xbd6dbcc4,0x3d35bd35,0x3cc43d6d,
0x3d0e3d55,0xbd7b3c48,0x3c48bd7b,0x3d553d0e,0x3d800000,0xbcc43d6d,0xbd35bd35,0x3d6dbcc4,0x3d55bd0e,0x3c483d7b,0xbd7bbc48,0x3d0ebd55,0x8000bd80,0x3d6d3cc4,0xbd353d35,0xbcc4bd6d,
0x80003d80,0xbd800000,0x8000bd80,0x3d800000,0xbd353d35,0xbd35bd35,0x3d35bd35,0x3d353d35,0x80003d80,0xbd800000,0x8000bd80,0x3d800000,0xbd353d35,0xbd35bd35,0x3d35bd35,0x3d353d35,
0x80003d80,0xbd800000,0x8000bd80,0x3d800000,0xbd353d35,0xbd35bd35,0x3d35bd35,0x3d353d35,0x80003d80,0xbd800000,0x8000bd80,0x3d800000,0xbd353d35,0xbd35bd35,0x3d35bd35,0x3d353d35,
0x3d0ebd55,0x3d7b3c48,0x3c483d7b,0xbd553d0e,0x8000bd80,0x3d6dbcc4,0x3d353d35,0xbcc43d6d,0xbd55bd0e,0x3c48bd7b,0x3d7bbc48,0x3d0e3d55,0xbd800000,0xbcc4bd6d,0x3d35bd35,0x3d6d3cc4,
0xbd0e3d55,0xbd7bbc48,0xbc48bd7b,0x3d55bd0e,0x80003d80,0xbd6d3cc4,0xbd35bd35,0x3cc4bd6d,0x3d553d0e,0xbc483d7b,0xbd7b3c48,0xbd0ebd55,0x3d800000,0x3cc43d6d,0xbd353d35,0xbd6dbcc4,
0x8000bd80,0x3d35bd35,0x3d800000,0x3d353d35,0x3cc4bd6d,0x3d6dbcc4,0x3d6d3cc4,0x3cc43d6d,0x80003d80,0xbd353d35,0xbd800000,0xbd35bd35,0xbcc43d6d,0xbd6d3cc4,0xbd6dbcc4,0xbcc4bd6d,
0x8000bd80,0x3d35bd35,0x3d800000,0x3d353d35,0x3cc4bd6d,0x3d6dbcc4,0x3d6d3cc4,0x3cc43d6d,0x80003d80,0xbd353d35,0xbd800000,0xbd35bd35,0xbcc43d6d,0xbd6d3cc4,0xbd6dbcc4,0xbcc4bd6d,
0x3d7b3c48,0x3d553d0e,0x3d0e3d55,0x3c483d7b,0x3d800000,0x3d6d3cc4,0x3d353d35,0x3cc43d6d,0x3c48bd7b,0x3d0ebd55,0x3d55bd0e,0x3d7bbc48,0x8000bd80,0x3cc4bd6d,0x3d35bd35,0x3d6dbcc4,
0xbd7bbc48,0xbd55bd0e,0xbd0ebd55,0xbc48bd7b,0xbd800000,0xbd6dbcc4,0xbd35bd35,0xbcc4bd6d,0xbc483d7b,0xbd0e3d55,0xbd553d0e,0xbd7b3c48,0x80003d80,0xbcc43d6d,0xbd353d35,0xbd6d3cc4,
0x3d800000,0xbd800000,0x3d800000,0xbd800000,0x3d80,0xbd80,0x3d80,0xbd80,0x3d800000,0xbd800000,0x3d800000,0xbd800000,0x3d80,0xbd80,0x3d80,0xbd80,
0x3d800000,0xbd800000,0x3d800000,0xbd800000,0x3d80,0xbd80,0x3d80,0xbd80,0x3d800000,0xbd800000,0x3d800000,0xbd800000,0x3d80,0xbd80,0x3d80,0xbd80,
0x3c483d7b,0xbd0ebd55,0x3d553d0e,0xbd7bbc48,0x3d800000,0xbd6d3cc4,0x3d35bd35,0xbcc43d6d,0x3d7bbc48,0xbd553d0e,0x3d0ebd55,0xbc483d7b,0xbd80,0x3cc43d6d,0xbd35bd35,0x3d6d3cc4,
0xbc48bd7b,0x3d0e3d55,0xbd55bd0e,0x3d7b3c48,0xbd800000,0x3d6dbcc4,0xbd353d35,0x3cc4bd6d,0xbd7b3c48,0x3d55bd0e,0xbd0e3d55,0x3c48bd7b,0x3d80,0xbcc4bd6d,0x3d353d35,0xbd6dbcc4,
0xbd800000,0x3d35bd35,0x3d80,0xbd35bd35,0xbcc4bd6d,0x3d6d3cc4,0xbd6d3cc4,0x3cc4bd6d,0x3d800000,0xbd353d35,0xbd80,0x3d353d35,0x3cc43d6d,0xbd6dbcc4,0x3d6dbcc4,0xbcc43d6d,
0xbd800000,0x3d35bd35,0x3d80,0xbd35bd35,0xbcc4bd6d,0x3d6d3cc4,0xbd6d3cc4,0x3cc4bd6d,0x3d800000,0xbd353d35,0xbd80,0x3d353d35,0x3cc43d6d,0xbd6dbcc4,0x3d6dbcc4,0xbcc43d6d,
0xbd553d0e,0xbc48bd7b,0x3d7b3c48,0xbd0e3d55,0x3d80,0xbd6dbcc4,0x3d35bd35,0x3cc43d6d,0x3d0e3d55,0xbd7b3c48,0x3c48bd7b,0x3d553d0e,0x3d800000,0xbcc43d6d,0xbd35bd35,0x3d6dbcc4,
0x3d55bd0e,0x3c483d7b,0xbd7bbc48,0x3d0ebd55,0xbd80,0x3d6d3cc4,0xbd353d35,0xbcc4bd6d,0xbd0ebd55,0x3d7bbc48,0xbc483d7b,0xbd55bd0e,0xbd800000,0x3cc4bd6d,0x3d353d35,0xbd6d3cc4,
0x3d800000,0x3d80,0xbd800000,0xbd80,0x3d353d35,0xbd353d35,0xbd35bd35,0x3d35bd35,0x3d800000,0x3d80,0xbd800000,0xbd80,0x3d353d35,0xbd353d35,0xbd35bd35,0x3d35bd35,
0x3d800000,0x3d80,0xbd800000,0xbd80,0x3d353d35,0xbd353d35,0xbd35bd35,0x3d35bd35,0x3d800000,0x3d80,0xbd800000,0xbd80,0x3d353d35,0xbd353d35,0xbd35bd35,0x3d35bd35,
0xbd55bd0e,0x3c48bd7b,0x3d7bbc48,0x3d0e3d55,0xbd800000,0xbcc4bd6d,0x3d35bd35,0x3d6d3cc4,0xbd0e3d55,0xbd7bbc48,0xbc48bd7b,0x3d55bd0e,0x3d80,0xbd6d3cc4,0xbd35bd35,0x3cc4bd6d,
0x3d553d0e,0xbc483d7b,0xbd7b3c48,0xbd0ebd55,0x3d800000,0x3cc43d6d,0xbd353d35,0xbd6dbcc4,0x3d0ebd55,0x3d7b3c48,0x3c483d7b,0xbd553d0e,0xbd80,0x3d6dbcc4,0x3d353d35,0xbcc43d6d,
0xbd800000,0xbd35bd35,0xbd80,0x3d35bd35,0xbd6dbcc4,0xbcc4bd6d,0x3cc4bd6d,0x3d6dbcc4,0x3d800000,0x3d353d35,0x3d80,0xbd353d35,0x3d6d3cc4,0x3cc43d6d,0xbcc43d6d,0xbd6d3cc4,
0xbd800000,0xbd35bd35,0xbd80,0x3d35bd35,0xbd6dbcc4,0xbcc4bd6d,0x3cc4bd6d,0x3d6dbcc4,0x3d800000,0x3d353d35,0x3d80,0xbd353d35,0x3d6d3cc4,0x3cc43d6d,0xbcc43d6d,0xbd6d3cc4,
0x3c48bd7b,0x3d0ebd55,0x3d55bd0e,0x3d7bbc48,0xbd80,0x3cc4bd6d,0x3d35bd35,0x3d6dbcc4,0xbd7bbc48,0xbd55bd0e,0xbd0ebd55,0xbc48bd7b,0xbd800000,0xbd6dbcc4,0xbd35bd35,0xbcc4bd6d,
0xbc483d7b,0xbd0e3d55,0xbd553d0e,0xbd7b3c48,0x3d80,0xbcc43d6d,0xbd353d35,0xbd6d3cc4,0x3d7b3c48,0x3d553d0e,0x3d0e3d55,0x3c483d7b,0x3d800000,0x3d6d3cc4,0x3d353d35,0x3cc43d6d,
0x3f003f00,0xbf003f00,0x3f003f00,0xbf003f00,0x3f003f00,0xbf003f00,0x3f003f00,0xbf003f00,0x3f003f00,0xbf003f00,0x3f003f00,0xbf003f00,0x3f003f00,0xbf003f00,0x3f003f00,0xbf003f00,
0x3eff3f00,0xbd490000,0x3ea23eb5,0xbec6beb5,0x3ef53efb,0xbe15bdc8,0x3e713e8e,0xbee2bed5,0x3ee23eed,0xbe71be44,0x3e153e44,0xbef5beed,0x3ec63ed5,0xbea2be8e,0x3d493dc8,0xbeffbefb,
0x3efb3f00,0xbdc80000,0xbdc80000,0xbefbbf00,0x3ed53eed,0xbe8ebe44,0xbe8ebe44,0xbed5beed,0x3e8e3eb5,0xbed5beb5,0xbed5beb5,0xbe8ebeb5,0x3dc83e44,0xbefbbeed,0xbefbbeed,0xbdc8be44,
0x3ef53f00,0xbe150000,0xbee2beb5,0xbe71beb5,0x3ea23ed5,0xbec6be8e,0xbeffbefb,0x3d49bdc8,0x3d493e44,0xbeffbeed,0xbec6beed,0x3ea23e44,0xbe71bdc8,0xbee2befb,0xbe15be8e,0x3ef53ed5,
0x3eed3f00,0xbe440000,0xbeedbf00,0x3e440000,0x3e443eb5,0xbeedbeb5,0xbe44beb5,0x3eed3eb5,0xbe440000,0xbeedbf00,0x3e440000,0x3eed3f00,0xbeedbeb5,0xbe44beb5,0x3eed3eb5,0x3e443eb5,
0x3ee23f00,0xbe710000,0xbe15beb5,0x3ef53eb5,0x3d493e8e,0xbeffbed5,0x3ea23dc8,0x3ec63efb,0xbec6be44,0xbea2beed,0x3eff3eed,0xbd493e44,0xbef5befb,0x3e15bdc8,0x3e713ed5,0xbee2be8e,
0x3ed53f00,0xbe8e0000,0x3e8e0000,0x3ed53f00,0xbdc83e44,0xbefbbeed,0x3efb3eed,0xbdc83e44,0xbefbbeb5,0xbdc8beb5,0x3dc83eb5,0xbefbbeb5,0xbe8ebeed,0x3ed53e44,0xbed5be44,0xbe8ebeed,
0x3ec63f00,0xbea20000,0x3eff3eb5,0x3d493eb5,0xbe713dc8,0xbee2befb,0x3e153ed5,0xbef5be8e,0xbef5beed,0x3e15be44,0xbee2be44,0xbe71beed,0x3d49be8e,0x3eff3ed5,0xbea2befb,0x3ec63dc8,
0x3eb53f00,0xbeb50000,0x3eb53f00,0xbeb50000,0xbeb50000,0xbeb5bf00,0xbeb50000,0xbeb5bf00,0xbeb5bf00,0x3eb50000,0xbeb5bf00,0x3eb50000,0x3eb50000,0x3eb53f00,0x3eb50000,0x3eb53f00,
0x3ea23f00,0xbec60000,0xbd493eb5,0xbeffbeb5,0xbee2bdc8,0xbe71befb,0xbef5bed5,0x3e15be8e,0xbe15beed,0x3ef53e44,0x3e71be44,0x3ee23eed,0x3eff3e8e,0x3d493ed5,0x3ec63efb,0xbea23dc8,
0x3e8e3f00,0xbed50000,0xbed50000,0xbe8ebf00,0xbefbbe44,0xbdc8beed,0xbdc8beed,0x3efb3e44,0x3dc8beb5,0x3efb3eb5,0x3efb3eb5,0xbdc83eb5,0x3ed53eed,0xbe8e3e44,0xbe8e3e44,0xbed5beed,
0x3e713f00,0xbee20000,0xbef5beb5,0x3e15beb5,0xbeffbe8e,0x3d49bed5,0x3ec6bdc8,0x3ea23efb,0x3ea2be44,0x3ec63eed,0x3d493eed,0xbeffbe44,0x3e153efb,0xbef5bdc8,0xbee2bed5,0x3e71be8e,
0x3e443f00,0xbeed0000,0xbe44bf00,0x3eed0000,0xbeedbeb5,0x3e44beb5,0x3eed3eb5,0xbe443eb5,0x3eed0000,0x3e443f00,0xbeed0000,0xbe44bf00,0xbe443eb5,0xbeedbeb5,0x3e44beb5,0x3eed3eb5,
0x3e153f00,0xbef50000,0x3e71beb5,0x3ee23eb5,0xbec6bed5,0x3ea2be8e,0x3d493efb,0xbeffbdc8,0x3eff3e44,0xbd493eed,0xbea2beed,0x3ec6be44,0xbee23dc8,0xbe71befb,0x3ef53e8e,0xbe153ed5,
0x3dc83f00,0xbefb0000,0x3efb0000,0x3dc83f00,0xbe8ebeed,0x3ed5be44,0xbed53e44,0xbe8ebeed,0x3ed53eb5,0xbe8e3eb5,0x3e8ebeb5,0x3ed53eb5,0xbefbbe44,0x3dc8beed,0xbdc83eed,0xbefbbe44,
0x3d493f00,0xbeff0000,0x3ec63eb5,0xbea23eb5,0xbe15befb,0x3ef5bdc8,0xbee2be8e,0x3e71bed5,0x3e713eed,0xbee23e44,0x3ef53e44,0xbe153eed,0xbea2bed5,0x3ec6be8e,0xbeffbdc8,0x3d49befb,
0x3f00,0xbf000000,0x3f00,0xbf000000,0xbf00,0x3f000000,0xbf00,0x3f000000,0x3f00,0xbf000000,0x3f00,0xbf000000,0xbf00,0x3f000000,0xbf00,0x3f000000,
0xbd493f00,0xbeff0000,0xbec63eb5,0xbea2beb5,0x3e15befb,0x3ef53dc8,0x3ee2be8e,0x3e713ed5,0xbe713eed,0xbee2be44,0xbef53e44,0xbe15beed,0x3ea2bed5,0x3ec63e8e,0x3effbdc8,0x3d493efb,
0xbdc83f00,0xbefb0000,0xbefb0000,0x3dc8bf00,0x3e8ebeed,0x3ed53e44,0x3ed53e44,0xbe8e3eed,0xbed53eb5,0xbe8ebeb5,0xbe8ebeb5,0x3ed5beb5,0x3efbbe44,0x3dc83eed,0x3dc83eed,0xbefb3e44,
0xbe153f00,0xbef50000,0xbe71beb5,0x3ee2beb5,0x3ec6bed5,0x3ea23e8e,0xbd493efb,0xbeff3dc8,0xbeff3e44,0xbd49beed,0x3ea2beed,0x3ec63e44,0x3ee23dc8,0xbe713efb,0xbef53e8e,0xbe15bed5,
0xbe443f00,0xbeed0000,0x3e44bf00,0x3eed0000,0x3eedbeb5,0x3e443eb5,0xbeed3eb5,0xbe44beb5,0xbeed0000,0x3e44bf00,0x3eed0000,0xbe443f00,0x3e443eb5,0xbeed3eb5,0xbe44beb5,0x3eedbeb5,
0xbe713f00,0xbee20000,0x3ef5beb5,0x3e153eb5,0x3effbe8e,0x3d493ed5,0xbec6bdc8,0x3ea2befb,0xbea2be44,0x3ec6beed,0xbd493eed,0xbeff3e44,0xbe153efb,0xbef53dc8,0x3ee2bed5,0x3e713e8e,
0xbe8e3f00,0xbed50000,0x3ed50000,0xbe8e3f00,0x3efbbe44,0xbdc83eed,0x3dc8beed,0x3efbbe44,0xbdc8beb5,0x3efbbeb5,0xbefb3eb5,0xbdc8beb5,0xbed53eed,0xbe8ebe44,0x3e8e3e44,0xbed53eed,
0xbea23f00,0xbec60000,0x3d493eb5,0xbeff3eb5,0x3ee2bdc8,0xbe713efb,0x3ef5bed5,0x3e153e8e,0x3e15beed,0x3ef5be44,0xbe71be44,0x3ee2beed,0xbeff3e8e,0x3d49bed5,0xbec63efb,0xbea2bdc8,
0xbeb53f00,0xbeb50000,0xbeb53f00,0xbeb50000,0x3eb50000,0xbeb53f00,0x3eb50000,0xbeb53f00,0x3eb5bf00,0x3eb50000,0x3eb5bf00,0x3eb50000,0xbeb50000,0x3eb5bf00,0xbeb50000,0x3eb5bf00,
0xbec63f00,0xbea20000,0xbeff3eb5,0x3d49beb5,0x3e713dc8,0xbee23efb,0xbe153ed5,0xbef53e8e,0x3ef5beed,0x3e153e44,0x3ee2be44,0xbe713eed,0xbd49be8e,0x3effbed5,0x3ea2befb,0x3ec6bdc8,
0xbed53f00,0xbe8e0000,0xbe8e0000,0x3ed5bf00,0x3dc83e44,0xbefb3eed,0xbefb3eed,0xbdc8be44,0x3efbbeb5,0xbdc83eb5,0xbdc83eb5,0xbefb3eb5,0x3e8ebeed,0x3ed5be44,0x3ed5be44,0xbe8e3eed,
0xbee23f00,0xbe710000,0x3e15beb5,0x3ef5beb5,0xbd493e8e,0xbeff3ed5,0xbea23dc8,0x3ec6befb,0x3ec6be44,0xbea23eed,0xbeff3eed,0xbd49be44,0x3ef5befb,0x3e153dc8,0xbe713ed5,0xbee23e8e,
0xbeed3f00,0xbe440000,0x3eedbf00,0x3e440000,0xbe443eb5,0xbeed3eb5,0x3e44beb5,0x3eedbeb5,0x3e440000,0xbeed3f00,0xbe440000,0x3eedbf00,0x3eedbeb5,0xbe443eb5,0xbeed3eb5,0x3e44beb5,
0xbef53f00,0xbe150000,0x3ee2beb5,0xbe713eb5,0xbea23ed5,0xbec63e8e,0x3effbefb,0x3d493dc8,0xbd493e44,0xbeff3eed,0x3ec6beed,0x3ea2be44,0x3e71bdc8,0xbee23efb,0x3e15be8e,0x3ef5bed5,
0xbefb3f00,0xbdc80000,0x3dc80000,0xbefb3f00,0xbed53eed,0xbe8e3e44,0x3e8ebe44,0xbed53eed,0xbe8e3eb5,0xbed53eb5,0x3ed5beb5,0xbe8e3eb5,0xbdc83e44,0xbefb3eed,0x3efbbeed,0xbdc83e44,
0xbeff3f00,0xbd490000,0xbea23eb5,0xbec63eb5,0xbef53efb,0xbe153dc8,0xbe713e8e,0xbee23ed5,0xbee23eed,0xbe713e44,0xbe153e44,0xbef53eed,0xbec63ed5,0xbea23e8e,0xbd493dc8,0xbeff3efb,
0x3f003f00,0xbf003f00,0x3f003f00,0xbf003f00,0x3f003f00,0xbf003f00,0x3f003f00,0xbf003f00,0x3f003f00,0xbf003f00,0x3f003f00,0xbf003f00,0x3f003f00,0xbf003f00,0x3f003f00,0xbf003f00,
0xbd490000,0xbeffbf00,0xbec6beb5,0xbea2beb5,0xbe15bdc8,0xbef5befb,0xbee2bed5,0xbe71be8e,0xbe71be44,0xbee2beed,0xbef5beed,0xbe15be44,0xbea2be8e,0xbec6bed5,0xbeffbefb,0xbd49bdc8,
0xbefbbf00,0x3dc80000,0x3dc80000,0x3efb3f00,0xbed5beed,0x3e8e3e44,0x3e8e3e44,0x3ed53eed,0xbe8ebeb5,0x3ed53eb5,0x3ed53eb5,0x3e8e3eb5,0xbdc8be44,0x3efb3eed,0x3efb3eed,0x3dc83e44,
0x3e150000,0x3ef53f00,0x3e713eb5,0xbee2beb5,0x3ec63e8e,0x3ea23ed5,0xbd493dc8,0xbeffbefb,0x3eff3eed,0x3d493e44,0xbea2be44,0xbec6beed,0x3ee23efb,0xbe71bdc8,0xbef5bed5,0xbe15be8e,
0x3eed3f00,0xbe440000,0xbeedbf00,0x3e440000,0x3e443eb5,0xbeedbeb5,0xbe44beb5,0x3eed3eb5,0xbe440000,0xbeedbf00,0x3e440000,0x3eed3f00,0xbeedbeb5,0xbe44beb5,0x3eed3eb5,0x3e443eb5,
0xbe710000,0xbee2bf00,0x3ef53eb5,0x3e153eb5,0xbeffbed5,0xbd49be8e,0x3ec63efb,0xbea2bdc8,0xbea2beed,0x3ec63e44,0xbd493e44,0xbeffbeed,0x3e15bdc8,0x3ef53efb,0xbee2be8e,0xbe71bed5,
0xbed5bf00,0x3e8e0000,0xbe8e0000,0xbed5bf00,0x3dc8be44,0x3efb3eed,0xbefbbeed,0x3dc8be44,0x3efb3eb5,0x3dc83eb5,0xbdc8beb5,0x3efb3eb5,0x3e8e3eed,0xbed5be44,0x3ed53e44,0x3e8e3eed,
0x3ea20000,0x3ec63f00,0xbd49beb5,0x3eff3eb5,0x3ee23efb,0xbe713dc8,0x3ef53e8e,0x3e153ed5,0xbe153e44,0xbef5beed,0x3e713eed,0xbee2be44,0xbeffbed5,0x3d49be8e,0xbec6bdc8,0xbea2befb,
0x3eb53f00,0xbeb50000,0x3eb53f00,0xbeb50000,0xbeb50000,0xbeb5bf00,0xbeb50000,0xbeb5bf00,0xbeb5bf00,0x3eb50000,0xbeb5bf00,0x3eb50000,0x3eb50000,0x3eb53f00,0x3eb50000,0x3eb53f00,
0xbec60000,0xbea2bf00,0xbeffbeb5,0x3d49beb5,0xbe71befb,0x3ee23dc8,0x3e15be8e,0x3ef53ed5,0x3ef53e44,0x3e153eed,0x3ee23eed,0xbe713e44,0x3d493ed5,0xbeffbe8e,0xbea23dc8,0xbec6befb,
0xbe8ebf00,0x3ed50000,0x3ed50000,0x3e8e3f00,0x3efb3e44,0x3dc83eed,0x3dc83eed,0xbefbbe44,0xbdc83eb5,0xbefbbeb5,0xbefbbeb5,0x3dc8beb5,0xbed5beed,0x3e8ebe44,0x3e8ebe44,0x3ed53eed,
0x3ee20000,0x3e713f00,0xbe153eb5,0xbef5beb5,0xbd493ed5,0xbeffbe8e,0xbea2befb,0x3ec6bdc8,0xbec6beed,0x3ea2be44,0x3eff3e44,0x3d493eed,0x3ef53dc8,0x3e153efb,0xbe713e8e,0xbee2bed5,
0x3e443f00,0xbeed0000,0xbe44bf00,0x3eed0000,0xbeedbeb5,0x3e44beb5,0x3eed3eb5,0xbe443eb5,0x3eed0000,0x3e443f00,0xbeed0000,0xbe44bf00,0xbe443eb5,0xbeedbeb5,0x3e44beb5,0x3eed3eb5,
0xbef50000,0xbe15bf00,0x3ee23eb5,0xbe713eb5,0x3ea2be8e,0x3ec63ed5,0xbeffbdc8,0xbd49befb,0xbd493eed,0xbeffbe44,0x3ec6be44,0x3ea23eed,0xbe71befb,0x3ee2bdc8,0xbe153ed5,0xbef5be8e,
0xbdc8bf00,0x3efb0000,0xbefb0000,0xbdc8bf00,0x3e8e3eed,0xbed53e44,0x3ed5be44,0x3e8e3eed,0xbed5beb5,0x3e8ebeb5,0xbe8e3eb5,0xbed5beb5,0x3efb3e44,0xbdc83eed,0x3dc8beed,0x3efb3e44,
0x3eff0000,0x3d493f00,0x3ea2beb5,0x3ec63eb5,0xbef53dc8,0xbe15befb,0xbe713ed5,0xbee2be8e,0x3ee2be44,0x3e713eed,0x3e15beed,0x3ef53e44,0xbec63e8e,0xbea2bed5,0xbd493efb,0xbeffbdc8,
0x3f00,0xbf000000,0x3f00,0xbf000000,0xbf00,0x3f000000,0xbf00,0x3f000000,0x3f00,0xbf000000,0x3f00,0xbf000000,0xbf00,0x3f000000,0xbf00,0x3f000000,
0xbeff0000,0x3d49bf00,0xbea2beb5,0x3ec6beb5,0x3ef53dc8,0xbe153efb,0x3e713ed5,0xbee23e8e,0xbee2be44,0x3e71beed,0xbe15beed,0x3ef5be44,0x3ec63e8e,0xbea23ed5,0x3d493efb,0xbeff3dc8,
0x3dc8bf00,0x3efb0000,0x3efb0000,0xbdc83f00,0xbe8e3eed,0xbed5be44,0xbed5be44,0x3e8ebeed,0x3ed5beb5,0x3e8e3eb5,0x3e8e3eb5,0xbed53eb5,0xbefb3e44,0xbdc8beed,0xbdc8beed,0x3efbbe44,
0x3ef50000,0xbe153f00,0xbee23eb5,0xbe71beb5,0xbea2be8e,0x3ec6bed5,0x3effbdc8,0xbd493efb,0x3d493eed,0xbeff3e44,0xbec6be44,0x3ea2beed,0x3e71befb,0x3ee23dc8,0x3e153ed5,0xbef53e8e,
0xbe443f00,0xbeed0000,0x3e44bf00,0x3eed0000,0x3eedbeb5,0x3e443eb5,0xbeed3eb5,0xbe44beb5,0xbeed0000,0x3e44bf00,0x3eed0000,0xbe443f00,0x3e443eb5,0xbeed3eb5,0xbe44beb5,0x3eedbeb5,
0xbee20000,0x3e71bf00,0x3e153eb5,0xbef53eb5,0x3d493ed5,0xbeff3e8e,0x3ea2befb,0x3ec63dc8,0x3ec6beed,0x3ea23e44,0xbeff3e44,0x3d49beed,0xbef53dc8,0x3e15befb,0x3e713e8e,0xbee23ed5,
0x3e8ebf00,0x3ed50000,0xbed50000,0x3e8ebf00,0xbefb3e44,0x3dc8beed,0xbdc83eed,0xbefb3e44,0x3dc83eb5,0xbefb3eb5,0x3efbbeb5,0x3dc83eb5,0x3ed5beed,0x3e8e3e44,0xbe8ebe44,0x3ed5beed,
0x3ec60000,0xbea23f00,0x3effbeb5,0x3d493eb5,0x3e71befb,0x3ee2bdc8,0xbe15be8e,0x3ef5bed5,0xbef53e44,0x3e15beed,0xbee23eed,0xbe71be44,0xbd493ed5,0xbeff3e8e,0x3ea23dc8,0xbec63efb,
0xbeb53f00,0xbeb50000,0xbeb53f00,0xbeb50000,0x3eb50000,0xbeb53f00,0x3eb50000,0xbeb53f00,0x3eb5bf00,0x3eb50000,0x3eb5bf00,0x3eb50000,0xbeb50000,0x3eb5bf00,0xbeb50000,0x3eb5bf00,
0xbea20000,0x3ec6bf00,0x3d49beb5,0x3effbeb5,0xbee23efb,0xbe71bdc8,0xbef53e8e,0x3e15bed5,0x3e153e44,0xbef53eed,0xbe713eed,0xbee23e44,0x3effbed5,0x3d493e8e,0x3ec6bdc8,0xbea23efb,
0x3ed5bf00,0x3e8e0000,0x3e8e0000,0xbed53f00,0xbdc8be44,0x3efbbeed,0x3efbbeed,0x3dc83e44,0xbefb3eb5,0x3dc8beb5,0x3dc8beb5,0x3efbbeb5,0xbe8e3eed,0xbed53e44,0xbed53e44,0x3e8ebeed,
0x3e710000,0xbee23f00,0xbef53eb5,0x3e15beb5,0x3effbed5,0xbd493e8e,0xbec63efb,0xbea23dc8,0x3ea2beed,0x3ec6be44,0x3d493e44,0xbeff3eed,0xbe15bdc8,0x3ef5befb,0x3ee2be8e,0xbe713ed5,
0xbeed3f00,0xbe440000,0x3eedbf00,0x3e440000,0xbe443eb5,0xbeed3eb5,0x3e44beb5,0x3eedbeb5,0x3e440000,0xbeed3f00,0xbe440000,0x3eedbf00,0x3eedbeb5,0xbe443eb5,0xbeed3eb5,0x3e44beb5,
0xbe150000,0x3ef5bf00,0xbe713eb5,0xbee23eb5,0xbec63e8e,0x3ea2bed5,0x3d493dc8,0xbeff3efb,0xbeff3eed,0x3d49be44,0x3ea2be44,0xbec63eed,0xbee23efb,0xbe713dc8,0x3ef5bed5,0xbe153e8e,
0x3efbbf00,0x3dc80000,0xbdc80000,0x3efbbf00,0x3ed5beed,0x3e8ebe44,0xbe8e3e44,0x3ed5beed,0x3e8ebeb5,0x3ed5beb5,0xbed53eb5,0x3e8ebeb5,0x3dc8be44,0x3efbbeed,0xbefb3eed,0x3dc8be44,
0x3d490000,0xbeff3f00,0x3ec6beb5,0xbea23eb5,0x3e15bdc8,0xbef53efb,0x3ee2bed5,0xbe713e8e,0x3e71be44,0xbee23eed,0x3ef5beed,0xbe153e44,0x3ea2be8e,0xbec63ed5,0x3effbefb,0xbd493dc8,
0x3f003f00,0xbf003f00,0x3f003f00,0xbf003f00,0x3f003f00,0xbf003f00,0x3f003f00,0xbf003f00,0x3f003f00,0xbf003f00,0x3f003f00,0xbf003f00,0x3f003f00,0xbf003f00,0x3f003f00,0xbf003f00,
0xbeffbf00,0x3d490000,0xbea2beb5,0x3ec63eb5,0xbef5befb,0x3e153dc8,0xbe71be8e,0x3ee23ed5,0xbee2beed,0x3e713e44,0xbe15be44,0x3ef53eed,0xbec6bed5,0x3ea23e8e,0xbd49bdc8,0x3eff3efb,
0x3efb3f00,0xbdc80000,0xbdc80000,0xbefbbf00,0x3ed53eed,0xbe8ebe44,0xbe8ebe44,0xbed5beed,0x3e8e3eb5,0xbed5beb5,0xbed5beb5,0xbe8ebeb5,0x3dc83e44,0xbefbbeed,0xbefbbeed,0xbdc8be44,
0xbef5bf00,0x3e150000,0x3ee23eb5,0x3e713eb5,0xbea2bed5,0x3ec63e8e,0x3eff3efb,0xbd493dc8,0xbd49be44,0x3eff3eed,0x3ec63eed,0xbea2be44,0x3e713dc8,0x3ee23efb,0x3e153e8e,0xbef5bed5,
0x3eed3f00,0xbe440000,0xbeedbf00,0x3e440000,0x3e443eb5,0xbeedbeb5,0xbe44beb5,0x3eed3eb5,0xbe440000,0xbeedbf00,0x3e440000,0x3eed3f00,0xbeedbeb5,0xbe44beb5,0x3eed3eb5,0x3e443eb5,
0xbee2bf00,0x3e710000,0x3e153eb5,0xbef5beb5,0xbd49be8e,0x3eff3ed5,0xbea2bdc8,0xbec6befb,0x3ec63e44,0x3ea23eed,0xbeffbeed,0x3d49be44,0x3ef53efb,0xbe153dc8,0xbe71bed5,0x3ee23e8e,
0x3ed53f00,0xbe8e0000,0x3e8e0000,0x3ed53f00,0xbdc83e44,0xbefbbeed,0x3efb3eed,0xbdc83e44,0xbefbbeb5,0xbdc8beb5,0x3dc83eb5,0xbefbbeb5,0xbe8ebeed,0x3ed53e44,0xbed5be44,0xbe8ebeed,
0xbec6bf00,0x3ea20000,0xbeffbeb5,0xbd49beb5,0x3e71bdc8,0x3ee23efb,0xbe15bed5,0x3ef53e8e,0x3ef53eed,0xbe153e44,0x3ee23e44,0x3e713eed,0xbd493e8e,0xbeffbed5,0x3ea23efb,0xbec6bdc8,
0x3eb53f00,0xbeb50000,0x3eb53f00,0xbeb50000,0xbeb50000,0xbeb5bf00,0xbeb50000,0xbeb5bf00,0xbeb5bf00,0x3eb50000,0xbeb5bf00,0x3eb50000,0x3eb50000,0x3eb53f00,0x3eb50000,0x3eb53f00,
0xbea2bf00,0x3ec60000,0x3d49beb5,0x3eff3eb5,0x3ee23dc8,0x3e713efb,0x3ef53ed5,0xbe153e8e,0x3e153eed,0xbef5be44,0xbe713e44,0xbee2beed,0xbeffbe8e,0xbd49bed5,0xbec6befb,0x3ea2bdc8,
0x3e8e3f00,0xbed50000,0xbed50000,0xbe8ebf00,0xbefbbe44,0xbdc8beed,0xbdc8beed,0x3efb3e44,0x3dc8beb5,0x3efb3eb5,0x3efb3eb5,0xbdc83eb5,0x3ed53eed,0xbe8e3e44,0xbe8e3e44,0xbed5beed,
0xbe71bf00,0x3ee20000,0x3ef53eb5,0xbe153eb5,0x3eff3e8e,0xbd493ed5,0xbec63dc8,0xbea2befb,0xbea23e44,0xbec6beed,0xbd49beed,0x3eff3e44,0xbe15befb,0x3ef53dc8,0x3ee23ed5,0xbe713e8e,
0x3e443f00,0xbeed0000,0xbe44bf00,0x3eed0000,0xbeedbeb5,0x3e44beb5,0x3eed3eb5,0xbe443eb5,0x3eed0000,0x3e443f00,0xbeed0000,0xbe44bf00,0xbe443eb5,0xbeedbeb5,0x3e44beb5,0x3eed3eb5,
0xbe15bf00,0x3ef50000,0xbe713eb5,0xbee2beb5,0x3ec63ed5,0xbea23e8e,0xbd49befb,0x3eff3dc8,0xbeffbe44,0x3d49beed,0x3ea23eed,0xbec63e44,0x3ee2bdc8,0x3e713efb,0xbef5be8e,0x3e15bed5,
0x3dc83f00,0xbefb0000,0x3efb0000,0x3dc83f00,0xbe8ebeed,0x3ed5be44,0xbed53e44,0xbe8ebeed,0x3ed53eb5,0xbe8e3eb5,0x3e8ebeb5,0x3ed53eb5,0xbefbbe44,0x3dc8beed,0xbdc83eed,0xbefbbe44,
0xbd49bf00,0x3eff0000,0xbec6beb5,0x3ea2beb5,0x3e153efb,0xbef53dc8,0x3ee23e8e,0xbe713ed5,0xbe71beed,0x3ee2be44,0xbef5be44,0x3e15beed,0x3ea23ed5,0xbec63e8e,0x3eff3dc8,0xbd493efb,
0x3f00,0xbf000000,0x3f00,0xbf000000,0xbf00,0x3f000000,0xbf00,0x3f000000,0x3f00,0xbf000000,0x3f00,0xbf000000,0xbf00,0x3f000000,0xbf00,0x3f000000,
0x3d49bf00,0x3eff0000,0x3ec6beb5,0x3ea23eb5,0xbe153efb,0xbef5bdc8,0xbee23e8e,0xbe71bed5,0x3e71beed,0x3ee23e44,0x3ef5be44,0x3e153eed,0xbea23ed5,0xbec6be8e,0xbeff3dc8,0xbd49befb,
0xbdc83f00,0xbefb0000,0xbefb0000,0x3dc8bf00,0x3e8ebeed,0x3ed53e44,0x3ed53e44,0xbe8e3eed,0xbed53eb5,0xbe8ebeb5,0xbe8ebeb5,0x3ed5beb5,0x3efbbe44,0x3dc83eed,0x3dc83eed,0xbefb3e44,
0x3e15bf00,0x3ef50000,0x3e713eb5,0xbee23eb5,0xbec63ed5,0xbea2be8e,0x3d49befb,0x3effbdc8,0x3effbe44,0x3d493eed,0xbea23eed,0xbec6be44,0xbee2bdc8,0x3e71befb,0x3ef5be8e,0x3e153ed5,
0xbe443f00,0xbeed0000,0x3e44bf00,0x3eed0000,0x3eedbeb5,0x3e443eb5,0xbeed3eb5,0xbe44beb5,0xbeed0000,0x3e44bf00,0x3eed0000,0xbe443f00,0x3e443eb5,0xbeed3eb5,0xbe44beb5,0x3eedbeb5,
0x3e71bf00,0x3ee20000,0xbef53eb5,0xbe15beb5,0xbeff3e8e,0xbd49bed5,0x3ec63dc8,0xbea23efb,0x3ea23e44,0xbec63eed,0x3d49beed,0x3effbe44,0x3e15befb,0x3ef5bdc8,0xbee23ed5,0xbe71be8e,
0xbe8e3f00,0xbed50000,0x3ed50000,0xbe8e3f00,0x3efbbe44,0xbdc83eed,0x3dc8beed,0x3efbbe44,0xbdc8beb5,0x3efbbeb5,0xbefb3eb5,0xbdc8beb5,0xbed53eed,0xbe8ebe44,0x3e8e3e44,0xbed53eed,
0x3ea2bf00,0x3ec60000,0xbd49beb5,0x3effbeb5,0xbee23dc8,0x3e71befb,0xbef53ed5,0xbe15be8e,0xbe153eed,0xbef53e44,0x3e713e44,0xbee23eed,0x3effbe8e,0xbd493ed5,0x3ec6befb,0x3ea23dc8,
0xbeb53f00,0xbeb50000,0xbeb53f00,0xbeb50000,0x3eb50000,0xbeb53f00,0x3eb50000,0xbeb53f00,0x3eb5bf00,0x3eb50000,0x3eb5bf00,0x3eb50000,0xbeb50000,0x3eb5bf00,0xbeb50000,0x3eb5bf00,
0x3ec6bf00,0x3ea20000,0x3effbeb5,0xbd493eb5,0xbe71bdc8,0x3ee2befb,0x3e15bed5,0x3ef5be8e,0xbef53eed,0xbe15be44,0xbee23e44,0x3e71beed,0x3d493e8e,0xbeff3ed5,0xbea23efb,0xbec63dc8,
0xbed53f00,0xbe8e0000,0xbe8e0000,0x3ed5bf00,0x3dc83e44,0xbefb3eed,0xbefb3eed,0xbdc8be44,0x3efbbeb5,0xbdc83eb5,0xbdc83eb5,0xbefb3eb5,0x3e8ebeed,0x3ed5be44,0x3ed5be44,0xbe8e3eed,
0x3ee2bf00,0x3e710000,0xbe153eb5,0xbef53eb5,0x3d49be8e,0x3effbed5,0x3ea2bdc8,0xbec63efb,0xbec63e44,0x3ea2beed,0x3effbeed,0x3d493e44,0xbef53efb,0xbe15bdc8,0x3e71bed5,0x3ee2be8e,
0xbeed3f00,0xbe440000,0x3eedbf00,0x3e440000,0xbe443eb5,0xbeed3eb5,0x3e44beb5,0x3eedbeb5,0x3e440000,0xbeed3f00,0xbe440000,0x3eedbf00,0x3eedbeb5,0xbe443eb5,0xbeed3eb5,0x3e44beb5,
0x3ef5bf00,0x3e150000,0xbee23eb5,0x3e71beb5,0x3ea2bed5,0x3ec6be8e,0xbeff3efb,0xbd49bdc8,0x3d49be44,0x3effbeed,0xbec63eed,0xbea23e44,0xbe713dc8,0x3ee2befb,0xbe153e8e,0xbef53ed5,
0xbefb3f00,0xbdc80000,0x3dc80000,0xbefb3f00,0xbed53eed,0xbe8e3e44,0x3e8ebe44,0xbed53eed,0xbe8e3eb5,0xbed53eb5,0x3ed5beb5,0xbe8e3eb5,0xbdc83e44,0xbefb3eed,0x3efbbeed,0xbdc83e44,
0x3effbf00,0x3d490000,0x3ea2beb5,0x3ec6beb5,0x3ef5befb,0x3e15bdc8,0x3e71be8e,0x3ee2bed5,0x3ee2beed,0x3e71be44,0x3e15be44,0x3ef5beed,0x3ec6bed5,0x3ea2be8e,0x3d49bdc8,0x3effbefb,
0x3f003f00,0xbf003f00,0x3f003f00,0xbf003f00,0x3f003f00,0xbf003f00,0x3f003f00,0xbf003f00,0x3f003f00,0xbf003f00,0x3f003f00,0xbf003f00,0x3f003f00,0xbf003f00,0x3f003f00,0xbf003f00,
0x3d490000,0x3eff3f00,0x3ec63eb5,0x3ea23eb5,0x3e153dc8,0x3ef53efb,0x3ee23ed5,0x3e713e8e,0x3e713e44,0x3ee23eed,0x3ef53eed,0x3e153e44,0x3ea23e8e,0x3ec63ed5,0x3eff3efb,0x3d493dc8,
0xbefbbf00,0x3dc80000,0x3dc80000,0x3efb3f00,0xbed5beed,0x3e8e3e44,0x3e8e3e44,0x3ed53eed,0xbe8ebeb5,0x3ed53eb5,0x3ed53eb5,0x3e8e3eb5,0xbdc8be44,0x3efb3eed,0x3efb3eed,0x3dc83e44,
0xbe150000,0xbef5bf00,0xbe71beb5,0x3ee23eb5,0xbec6be8e,0xbea2bed5,0x3d49bdc8,0x3eff3efb,0xbeffbeed,0xbd49be44,0x3ea23e44,0x3ec63eed,0xbee2befb,0x3e713dc8,0x3ef53ed5,0x3e153e8e,
0x3eed3f00,0xbe440000,0xbeedbf00,0x3e440000,0x3e443eb5,0xbeedbeb5,0xbe44beb5,0x3eed3eb5,0xbe440000,0xbeedbf00,0x3e440000,0x3eed3f00,0xbeedbeb5,0xbe44beb5,0x3eed3eb5,0x3e443eb5,
0x3e710000,0x3ee23f00,0xbef5beb5,0xbe15beb5,0x3eff3ed5,0x3d493e8e,0xbec6befb,0x3ea23dc8,0x3ea23eed,0xbec6be44,0x3d49be44,0x3eff3eed,0xbe153dc8,0xbef5befb,0x3ee23e8e,0x3e713ed5,
0xbed5bf00,0x3e8e0000,0xbe8e0000,0xbed5bf00,0x3dc8be44,0x3efb3eed,0xbefbbeed,0x3dc8be44,0x3efb3eb5,0x3dc83eb5,0xbdc8beb5,0x3efb3eb5,0x3e8e3eed,0xbed5be44,0x3ed53e44,0x3e8e3eed,
0xbea20000,0xbec6bf00,0x3d493eb5,0xbeffbeb5,0xbee2befb,0x3e71bdc8,0xbef5be8e,0xbe15bed5,0x3e15be44,0x3ef53eed,0xbe71beed,0x3ee23e44,0x3eff3ed5,0xbd493e8e,0x3ec63dc8,0x3ea23efb,
0x3eb53f00,0xbeb50000,0x3eb53f00,0xbeb50000,0xbeb50000,0xbeb5bf00,0xbeb50000,0xbeb5bf00,0xbeb5bf00,0x3eb50000,0xbeb5bf00,0x3eb50000,0x3eb50000,0x3eb53f00,0x3eb50000,0x3eb53f00,
0x3ec60000,0x3ea23f00,0x3eff3eb5,0xbd493eb5,0x3e713efb,0xbee2bdc8,0xbe153e8e,0xbef5bed5,0xbef5be44,0xbe15beed,0xbee2beed,0x3e71be44,0xbd49bed5,0x3eff3e8e,0x3ea2bdc8,0x3ec63efb,
0xbe8ebf00,0x3ed50000,0x3ed50000,0x3e8e3f00,0x3efb3e44,0x3dc83eed,0x3dc83eed,0xbefbbe44,0xbdc83eb5,0xbefbbeb5,0xbefbbeb5,0x3dc8beb5,0xbed5beed,0x3e8ebe44,0x3e8ebe44,0x3ed53eed,
0xbee20000,0xbe71bf00,0x3e15beb5,0x3ef53eb5,0x3d49bed5,0x3eff3e8e,0x3ea23efb,0xbec63dc8,0x3ec63eed,0xbea23e44,0xbeffbe44,0xbd49beed,0xbef5bdc8,0xbe15befb,0x3e71be8e,0x3ee23ed5,
0x3e443f00,0xbeed0000,0xbe44bf00,0x3eed0000,0xbeedbeb5,0x3e44beb5,0x3eed3eb5,0xbe443eb5,0x3eed0000,0x3e443f00,0xbeed0000,0xbe44bf00,0xbe443eb5,0xbeedbeb5,0x3e44beb5,0x3eed3eb5,
0x3ef50000,0x3e153f00,0xbee2beb5,0x3e71beb5,0xbea23e8e,0xbec6bed5,0x3eff3dc8,0x3d493efb,0x3d49beed,0x3eff3e44,0xbec63e44,0xbea2beed,0x3e713efb,0xbee23dc8,0x3e15bed5,0x3ef53e8e,
0xbdc8bf00,0x3efb0000,0xbefb0000,0xbdc8bf00,0x3e8e3eed,0xbed53e44,0x3ed5be44,0x3e8e3eed,0xbed5beb5,0x3e8ebeb5,0xbe8e3eb5,0xbed5beb5,0x3efb3e44,0xbdc83eed,0x3dc8beed,0x3efb3e44,
0xbeff0000,0xbd49bf00,0xbea23eb5,0xbec6beb5,0x3ef5bdc8,0x3e153efb,0x3e71bed5,0x3ee23e8e,0xbee23e44,0xbe71beed,0xbe153eed,0xbef5be44,0x3ec6be8e,0x3ea23ed5,0x3d49befb,0x3eff3dc8,
0x3f00,0xbf000000,0x3f00,0xbf000000,0xbf00,0x3f000000,0xbf00,0x3f000000,0x3f00,0xbf000000,0x3f00,0xbf000000,0xbf00,0x3f000000,0xbf00,0x3f000000,
0x3eff0000,0xbd493f00,0x3ea23eb5,0xbec63eb5,0xbef5bdc8,0x3e15befb,0xbe71bed5,0x3ee2be8e,0x3ee23e44,0xbe713eed,0x3e153eed,0xbef53e44,0xbec6be8e,0x3ea2bed5,0xbd49befb,0x3effbdc8,
0x3dc8bf00,0x3efb0000,0x3efb0000,0xbdc83f00,0xbe8e3eed,0xbed5be44,0xbed5be44,0x3e8ebeed,0x3ed5beb5,0x3e8e3eb5,0x3e8e3eb5,0xbed53eb5,0xbefb3e44,0xbdc8beed,0xbdc8beed,0x3efbbe44,
0xbef50000,0x3e15bf00,0x3ee2beb5,0x3e713eb5,0x3ea23e8e,0xbec63ed5,0xbeff3dc8,0x3d49befb,0xbd49beed,0x3effbe44,0x3ec63e44,0xbea23eed,0xbe713efb,0xbee2bdc8,0xbe15bed5,0x3ef5be8e,
0xbe443f00,0xbeed0000,0x3e44bf00,0x3eed0000,0x3eedbeb5,0x3e443eb5,0xbeed3eb5,0xbe44beb5,0xbeed0000,0x3e44bf00,0x3eed0000,0xbe443f00,0x3e443eb5,0xbeed3eb5,0xbe44beb5,0x3eedbeb5,
0x3ee20000,0xbe713f00,0xbe15beb5,0x3ef5beb5,0xbd49bed5,0x3effbe8e,0xbea23efb,0xbec6bdc8,0xbec63eed,0xbea2be44,0x3effbe44,0xbd493eed,0x3ef5bdc8,0xbe153efb,0xbe71be8e,0x3ee2bed5,
0x3e8ebf00,0x3ed50000,0xbed50000,0x3e8ebf00,0xbefb3e44,0x3dc8beed,0xbdc83eed,0xbefb3e44,0x3dc83eb5,0xbefb3eb5,0x3efbbeb5,0x3dc83eb5,0x3ed5beed,0x3e8e3e44,0xbe8ebe44,0x3ed5beed,
0xbec60000,0x3ea2bf00,0xbeff3eb5,0xbd49beb5,0xbe713efb,0xbee23dc8,0x3e153e8e,0xbef53ed5,0x3ef5be44,0xbe153eed,0x3ee2beed,0x3e713e44,0x3d49bed5,0x3effbe8e,0xbea2bdc8,0x3ec6befb,
0xbeb53f00,0xbeb50000,0xbeb53f00,0xbeb50000,0x3eb50000,0xbeb53f00,0x3eb50000,0xbeb53f00,0x3eb5bf00,0x3eb50000,0x3eb5bf00,0x3eb50000,0xbeb50000,0x3eb5bf00,0xbeb50000,0x3eb5bf00,
0x3ea20000,0xbec63f00,0xbd493eb5,0xbeff3eb5,0x3ee2befb,0x3e713dc8,0x3ef5be8e,0xbe153ed5,0xbe15be44,0x3ef5beed,0x3e71beed,0x3ee2be44,0xbeff3ed5,0xbd49be8e,0xbec63dc8,0x3ea2befb,
0x3ed5bf00,0x3e8e0000,0x3e8e0000,0xbed53f00,0xbdc8be44,0x3efbbeed,0x3efbbeed,0x3dc83e44,0xbefb3eb5,0x3dc8beb5,0x3dc8beb5,0x3efbbeb5,0xbe8e3eed,0xbed53e44,0xbed53e44,0x3e8ebeed,
0xbe710000,0x3ee2bf00,0x3ef5beb5,0xbe153eb5,0xbeff3ed5,0x3d49be8e,0x3ec6befb,0x3ea2bdc8,0xbea23eed,0xbec63e44,0xbd49be44,0x3effbeed,0x3e153dc8,0xbef53efb,0xbee23e8e,0x3e71bed5,
0xbeed3f00,0xbe440000,0x3eedbf00,0x3e440000,0xbe443eb5,0xbeed3eb5,0x3e44beb5,0x3eedbeb5,0x3e440000,0xbeed3f00,0xbe440000,0x3eedbf00,0x3eedbeb5,0xbe443eb5,0xbeed3eb5,0x3e44beb5,
0x3e150000,0xbef53f00,0x3e71beb5,0x3ee2beb5,0x3ec6be8e,0xbea23ed5,0xbd49bdc8,0x3effbefb,0x3effbeed,0xbd493e44,0xbea23e44,0x3ec6beed,0x3ee2befb,0x3e71bdc8,0xbef53ed5,0x3e15be8e,
0x3efbbf00,0x3dc80000,0xbdc80000,0x3efbbf00,0x3ed5beed,0x3e8ebe44,0xbe8e3e44,0x3ed5beed,0x3e8ebeb5,0x3ed5beb5,0xbed53eb5,0x3e8ebeb5,0x3dc8be44,0x3efbbeed,0xbefb3eed,0x3dc8be44,
0xbd490000,0x3effbf00,0xbec63eb5,0x3ea2beb5,0xbe153dc8,0x3ef5befb,0xbee23ed5,0x3e71be8e,0xbe713e44,0x3ee2beed,0xbef53eed,0x3e15be44,0xbea23e8e,0x3ec6bed5,0xbeff3efb,0x3d49bdc8,
0x3f800000,0x0,0x3f800000,0x0,0x3f800000,0x0,0x3f800000,0x0,0x3f800000,0x0,0x3f800000,0x0,0x3f800000,0x0,0x3f800000,0x0,
0x3f800000,0x0,0x3f7ffec4,0xbbc90f88,0x3f7ffb11,0xbc490e90,0x3f7ff4e6,0xbc96c9b6,0x3f7fec43,0xbcc90ab0,0x3f7fe129,0xbcfb49ba,0x3f7fd397,0xbd16c32c,0x3f7fc38f,0xbd2fe007,
0x3f800000,0x0,0x3f7ffb11,0xbc490e90,0x3f7fec43,0xbcc90ab0,0x3f7fd397,0xbd16c32c,0x3f7fb10f,0xbd48fb30,0x3f7f84ab,0xbd7b2b74,0x3f7f4e6d,0xbd96a905,0x3f7f0e58,0xbdafb680,
0x3f800000,0x0,0x3f7ff4e6,0xbc96c9b6,0x3f7fd397,0xbd16c32c,0x3f7f9c18,0xbd621469,0x3f7f4e6d,0xbd96a905,0x3f7eea9d,0xbdbc3ac3,0x3f7e70b0,0xbde1bc2e,0x3f7de0b1,0xbe039502,
0x3f800000,0x0,0x3f7fec43,0xbcc90ab0,0x3f7fb10f,0xbd48fb30,0x3f7f4e6d,0xbd96a905,0x3f7ec46d,0xbdc8bd36,0x3f7e1324,0xbdfab273,0x3f7d3aac,0xbe164083,0x3f7c3b28,0xbe2f10a2,
0x3f800000,0x0,0x3f7fe129,0xbcfb49ba,0x3f7f84ab,0xbd7b2b74,0x3f7eea9d,0xbdbc3ac3,0x3f7e1324,0xbdfab273,0x3f7cfe73,0xbe1c76de,0x3f7baccd,0xbe3b6ecf,0x3f7a1e84,0xbe5a3997,
0x3f800000,0x0,0x3f7fd397,0xbd16c32c,0x3f7f4e6d,0xbd96a905,0x3f7e70b0,0xbde1bc2e,0x3f7d3aac,0xbe164083,0x3f7baccd,0xbe3b6ecf,0x3f79c79d,0xbe605c13,0x3f778bc5,0xbe827dc0,
0x3f800000,0x0,0x3f7fc38f,0xbd2fe007,0x3f7f0e58,0xbdafb680,0x3f7de0b1,0xbe039502,0x3f7c3b28,0xbe2f10a2,0x3f7a1e84,0xbe5a3997,0x3f778bc5,0xbe827dc0,0x3f748422,0xbe97a117,
0x3f800000,0x0,0x3f7fb10f,0xbd48fb30,0x3f7ec46d,0xbdc8bd36,0x3f7d3aac,0xbe164083,0x3f7b14be,0xbe47c5c2,0x3f7853f8,0xbe78cfcc,0x3f74fa0b,0xbe94a031,0x3f710908,0xbeac7cd4,
0x3f800000,0x0,0x3f7f9c18,0xbd621469,0x3f7e70b0,0xbde1bc2e,0x3f7c7eb0,0xbe28defc,0x3f79c79d,0xbe605c13,0x3f764d97,0xbe8b9507,0x3f721352,0xbea68f12,0x3f6d1c1d,0xbec1071e,
0x3f800000,0x0,0x3f7f84ab,0xbd7b2b74,0x3f7e1324,0xbdfab273,0x3f7baccd,0xbe3b6ecf,0x3f7853f8,0xbe78cfcc,0x3f740bdd,0xbe9aa086,0x3f6ed89e,0xbeb8442a,0x3f68bf3c,0xbed53641,
0x3f800000,0x0,0x3f7f6ac7,0xbd8a200a,0x3f7dabcc,0xbe09cf86,0x3f7ac516,0xbe4dee60,0x3f76ba07,0xbe888e93,0x3f718f57,0xbea986c4,0x3f6b4b0c,0xbec9b953,0x3f63f473,0xbee900b7,
0x3f800000,0x0,0x3f7f4e6d,0xbd96a905,0x3f7d3aac,0xbe164083,0x3f79c79d,0xbe605c13,0x3f74fa0b,0xbe94a031,0x3f6ed89e,0xbeb8442a,0x3f676bd8,0xbedae880,0x3f5ebe05,0xbefc5d27,
0x3f800000,0x0,0x3f7f2f9d,0xbda3308c,0x3f7cbfc9,0xbe22abb6,0x3f78b47b,0xbe72b651,0x3f731447,0xbea09ae5,0x3f6be858,0xbec6d529,0x3f633c5a,0xbeebcbbb,0x3f591e6a,0xbf07a136,
0x3f800000,0x0,0x3f7f0e58,0xbdafb680,0x3f7c3b28,0xbe2f10a2,0x3f778bc5,0xbe827dc0,0x3f710908,0xbeac7cd4,0x3f68bf3c,0xbed53641,0x3f5ebe05,0xbefc5d27,0x3f531849,0xbf10d3cd,
0x3f800000,0x0,0x3f7eea9d,0xbdbc3ac3,0x3f7baccd,0xbe3b6ecf,0x3f764d97,0xbe8b9507,0x3f6ed89e,0xbeb8442a,0x3f655e0b,0xbee363fa,0x3f59f26a,0xbf064b82,0x3f4cae79,0xbf19c200,
0x3f800000,0x0,0x3f7ec46d,0xbdc8bd36,0x3f7b14be,0xbe47c5c2,0x3f74fa0b,0xbe94a031,0x3f6c835e,0xbec3ef15,0x3f61c598,0xbef15aea,0x3f54db31,0xbf0e39da,0x3f45e403,0xbf226799,
0x3f800000,0x0,0x3f7e9bc9,0xbdd53db9,0x3f7a7302,0xbe541501,0x3f73913f,0xbe9d9e78,0x3f6a09a7,0xbecf7bca,0x3f5df6be,0xbeff17b2,0x3f4f7a1f,0xbf15f6d9,0x3f3ebc1b,0xbf2ac082,
0x3f800000,0x0,0x3f7e70b0,0xbde1bc2e,0x3f79c79d,0xbe605c13,0x3f721352,0xbea68f12,0x3f676bd8,0xbedae880,0x3f59f26a,0xbf064b82,0x3f49d112,0xbf1d7fd1,0x3f373a23,0xbf32c8c9,
0x3f800000,0x0,0x3f7e4323,0xbdee3876,0x3f791298,0xbe6c9a7f,0x3f708066,0xbeaf713a,0x3f64aa59,0xbee63375,0x3f55b993,0xbf0cead0,0x3f43e200,0xbf24d225,0x3f2f61a5,0xbf3a7ca4,
0x3f800000,0x0,0x3f7e1324,0xbdfab273,0x3f7853f8,0xbe78cfcc,0x3f6ed89e,0xbeb8442a,0x3f61c598,0xbef15aea,0x3f514d3d,0xbf13682a,0x3f3daef9,0xbf2beb4a,0x3f273656,0xbf41d870,
0x3f800000,0x0,0x3f7de0b1,0xbe039502,0x3f778bc5,0xbe827dc0,0x3f6d1c1d,0xbec1071e,0x3f5ebe05,0xbefc5d27,0x3f4cae79,0xbf19c200,0x3f373a23,0xbf32c8c9,0x3f1ebc12,0xbf48d8b3,
0x3f800000,0x0,0x3f7dabcc,0xbe09cf86,0x3f76ba07,0xbe888e93,0x3f6b4b0c,0xbec9b953,0x3f5b941a,0xbf039c3d,0x3f47de65,0xbf1ff6cb,0x3f3085bb,0xbf396842,0x3f15f6d9,0xbf4f7a1f,
0x3f800000,0x0,0x3f7d7474,0xbe1008b7,0x3f75dec6,0xbe8e9a22,0x3f696591,0xbed25a09,0x3f584853,0xbf08f59b,0x3f42de29,0xbf26050a,0x3f299415,0xbf3fc767,0x3f0cead0,0xbf55b993,
0x3f800000,0x0,0x3f7d3aac,0xbe164083,0x3f74fa0b,0xbe94a031,0x3f676bd8,0xbedae880,0x3f54db31,0xbf0e39da,0x3f3daef9,0xbf2beb4a,0x3f226799,0xbf45e403,0x3f039c3d,0xbf5b941a,
0x3f800000,0x0,0x3f7cfe73,0xbe1c76de,0x3f740bdd,0xbe9aa086,0x3f655e0b,0xbee363fa,0x3f514d3d,0xbf13682a,0x3f385216,0xbf31a81d,0x3f1b02c6,0xbf4bbbf8,0x3ef41f07,0xbf6106f2,
0x3f800000,0x0,0x3f7cbfc9,0xbe22abb6,0x3f731447,0xbea09ae5,0x3f633c5a,0xbeebcbbb,0x3f4d9f02,0xbf187fc0,0x3f32c8c9,0xbf373a23,0x3f13682a,0xbf514d3d,0x3ee0924f,0xbf660f88,
0x3f800000,0x0,0x3f7c7eb0,0xbe28defc,0x3f721352,0xbea68f12,0x3f6106f2,0xbef41f07,0x3f49d112,0xbf1d7fd1,0x3f2d1469,0xbf3ca003,0x3f0b9a6b,0xbf5695e5,0x3ecc9b8b,0xbf6aab7b,
0x3f800000,0x0,0x3f7c3b28,0xbe2f10a2,0x3f710908,0xbeac7cd4,0x3f5ebe05,0xbefc5d27,0x3f45e403,0xbf226799,0x3f273656,0xbf41d870,0x3f039c3d,0xbf5b941a,0x3eb8442a,0xbf6ed89e,
0x3f800000,0x0,0x3f7bf531,0xbe354098,0x3f6ff573,0xbeb263ef,0x3f5c61c7,0xbf0242b1,0x3f41d870,0xbf273656,0x3f212ff9,0xbf46e22a,0x3ef6e0cb,0xbf604621,0x3ea395c5,0xbf7294f8,
0x3f800000,0x0,0x3f7baccd,0xbe3b6ecf,0x3f6ed89e,0xbeb8442a,0x3f59f26a,0xbf064b82,0x3f3daef9,0xbf2beb4a,0x3f1b02c6,0xbf4bbbf8,0x3ee63375,0xbf64aa59,0x3e8e9a22,0xbf75dec6,
0x3f800000,0x0,0x3f7b61fc,0xbe419b37,0x3f6db293,0xbebe1d4a,0x3f577026,0xbf0a48ad,0x3f396842,0xbf3085bb,0x3f14b039,0xbf5064af,0x3ed53641,0xbf68bf3c,0x3e72b651,0xbf78b47b,
0x3f800000,0x0,0x3f800000,0x0,0x3f800000,0x0,0x3f800000,0x0,0x3f800000,0x0,0x3f800000,0x0,0x3f800000,0x0,0x3f800000,0x0,
0x3f7fb10f,0xbd48fb30,0x3f7f9c18,0xbd621469,0x3f7f84ab,0xbd7b2b74,0x3f7f6ac7,0xbd8a200a,0x3f7f4e6d,0xbd96a905,0x3f7f2f9d,0xbda3308c,0x3f7f0e58,0xbdafb680,0x3f7eea9d,0xbdbc3ac3,
0x3f7ec46d,0xbdc8bd36,0x3f7e70b0,0xbde1bc2e,0x3f7e1324,0xbdfab273,0x3f7dabcc,0xbe09cf86,0x3f7d3aac,0xbe164083,0x3f7cbfc9,0xbe22abb6,0x3f7c3b28,0xbe2f10a2,0x3f7baccd,0xbe3b6ecf,
0x3f7d3aac,0xbe164083,0x3f7c7eb0,0xbe28defc,0x3f7baccd,0xbe3b6ecf,0x3f7ac516,0xbe4dee60,0x3f79c79d,0xbe605c13,0x3f78b47b,0xbe72b651,0x3f778bc5,0xbe827dc0,0x3f764d97,0xbe8b9507,
0x3f7b14be,0xbe47c5c2,0x3f79c79d,0xbe605c13,0x3f7853f8,0xbe78cfcc,0x3f76ba07,0xbe888e93,0x3f74fa0b,0xbe94a031,0x3f731447,0xbea09ae5,0x3f710908,0xbeac7cd4,0x3f6ed89e,0xbeb8442a,
0x3f7853f8,0xbe78cfcc,0x3f764d97,0xbe8b9507,0x3f740bdd,0xbe9aa086,0x3f718f57,0xbea986c4,0x3f6ed89e,0xbeb8442a,0x3f6be858,0xbec6d529,0x3f68bf3c,0xbed53641,0x3f655e0b,0xbee363fa,
0x3f74fa0b,0xbe94a031,0x3f721352,0xbea68f12,0x3f6ed89e,0xbeb8442a,0x3f6b4b0c,0xbec9b953,0x3f676bd8,0xbedae880,0x3f633c5a,0xbeebcbbb,0x3f5ebe05,0xbefc5d27,0x3f59f26a,0xbf064b82,
0x3f710908,0xbeac7cd4,0x3f6d1c1d,0xbec1071e,0x3f68bf3c,0xbed53641,0x3f63f473,0xbee900b7,0x3f5ebe05,0xbefc5d27,0x3f591e6a,0xbf07a136,0x3f531849,0xbf10d3cd,0x3f4cae79,0xbf19c200,
0x3f6c835e,0xbec3ef15,0x3f676bd8,0xbedae880,0x3f61c598,0xbef15aea,0x3f5b941a,0xbf039c3d,0x3f54db31,0xbf0e39da,0x3f4d9f02,0xbf187fc0,0x3f45e403,0xbf226799,0x3f3daef9,0xbf2beb4a,
0x3f676bd8,0xbedae880,0x3f6106f2,0xbef41f07,0x3f59f26a,0xbf064b82,0x3f5233c6,0xbf121eb0,0x3f49d112,0xbf1d7fd1,0x3f40d0da,0xbf286605,0x3f373a23,0xbf32c8c9,0x3f2d1469,0xbf3ca003,
0x3f61c598,0xbef15aea,0x3f59f26a,0xbf064b82,0x3f514d3d,0xbf13682a,0x3f47de65,0xbf1ff6cb,0x3f3daef9,0xbf2beb4a,0x3f32c8c9,0xbf373a23,0x3f273656,0xbf41d870,0x3f1b02c6,0xbf4bbbf8,
0x3f5b941a,0xbf039c3d,0x3f5233c6,0xbf121eb0,0x3f47de65,0xbf1ff6cb,0x3f3ca003,0xbf2d1469,0x3f3085bb,0xbf396842,0x3f239da9,0xbf44e3f5,0x3f15f6d9,0xbf4f7a1f,0x3f07a136,0xbf591e6a,
0x3f54db31,0xbf0e39da,0x3f49d112,0xbf1d7fd1,0x3f3daef9,0xbf2beb4a,0x3f3085bb,0xbf396842,0x3f226799,0xbf45e403,0x3f13682a,0xbf514d3d,0x3f039c3d,0xbf5b941a,0x3ee63375,0xbf64aa59,
0x3f4d9f02,0xbf187fc0,0x3f40d0da,0xbf286605,0x3f32c8c9,0xbf373a23,0x3f239da9,0xbf44e3f5,0x3f13682a,0xbf514d3d,0x3f0242b1,0xbf5c61c7,0x3ee0924f,0xbf660f88,0x3ebb31a0,0xbf6e46be,
0x3f45e403,0xbf226799,0x3f373a23,0xbf32c8c9,0x3f273656,0xbf41d870,0x3f15f6d9,0xbf4f7a1f,0x3f039c3d,0xbf5b941a,0x3ee0924f,0xbf660f88,0x3eb8442a,0xbf6ed89e,0x3e8e9a22,0xbf75dec6,
0x3f3daef9,0xbf2beb4a,0x3f2d1469,0xbf3ca003,0x3f1b02c6,0xbf4bbbf8,0x3f07a136,0xbf591e6a,0x3ee63375,0xbf64aa59,0x3ebb31a0,0xbf6e46be,0x3e8e9a22,0xbf75dec6,0x3e419b37,0xbf7b61fc,
0x3f3504f3,0xbf3504f3,0x3f226799,0xbf45e403,0x3f0e39da,0xbf54db31,0x3ef15aea,0xbf61c598,0x3ec3ef15,0xbf6c835e,0x3e94a031,0xbf74fa0b,0x3e47c5c2,0xbf7b14be,0x3dc8bd36,0xbf7ec46d,
0x3f2beb4a,0xbf3daef9,0x3f173c07,0xbf4e8d90,0x3f00e7e4,0xbf5d2d53,0x3ed25a09,0xbf696591,0x3ea09ae5,0xbf731447,0x3e5a3997,0xbf7a1e84,0x3de1bc2e,0xbf7e70b0,0x3bc90f88,0xbf7ffec4,
0x3f226799,0xbf45e403,0x3f0b9a6b,0xbf5695e5,0x3ee63375,0xbf64aa59,0x3eb263ef,0xbf6ff573,0x3e78cfcc,0xbf7853f8,0x3e09cf86,0xbf7dabcc,0x3cc90ab0,0xbf7fec43,0xbdafb680,0xbf7f0e58,
0x3f187fc0,0xbf4d9f02,0x3eff17b2,0xbf5df6be,0x3ec9b953,0xbf6b4b0c,0x3e919ddd,0xbf756d97,0x3e2f10a2,0xbf7c3b28,0x3d621469,0xbf7f9c18,0xbd7b2b74,0xbf7f84ab,0xbe354098,0xbf7bf531,
0x3f0e39da,0xbf54db31,0x3ee63375,0xbf64aa59,0x3eac7cd4,0xbf710908,0x3e605c13,0xbf79c79d,0x3dc8bd36,0xbf7ec46d,0xbcc90ab0,0xbf7fec43,0xbe164083,0xbf7d3aac,0xbe888e93,0xbf76ba07,
0x3f039c3d,0xbf5b941a,0x3ecc9b8b,0xbf6aab7b,0x3e8e9a22,0xbf75dec6,0x3e1c76de,0xbf7cfe73,0x3cc90ab0,0xbf7fec43,0xbdd53db9,0xbf7e9bc9,0xbe6c9a7f,0xbf791298,0xbeb554ec,0xbf6f6830,
0x3ef15aea,0xbf61c598,0x3eb263ef,0xbf6ff573,0x3e605c13,0xbf79c79d,0x3dafb680,0xbf7f0e58,0xbd48fb30,0xbf7fb10f,0xbe3b6ecf,0xbf7baccd,0xbea09ae5,0xbf731447,0xbee0924f,0xbf660f88,
0x3edae880,0xbf676bd8,0x3e97a117,0xbf748422,0x3e22abb6,0xbf7cbfc9,0x3c96c9b6,0xbf7ff4e6,0xbdfab273,0xbf7e1324,0xbe8586ce,0xbf772417,0xbec9b953,0xbf6b4b0c,0xbf04f484,0xbf5ac450,
0x3ec3ef15,0xbf6c835e,0x3e78cfcc,0xbf7853f8,0x3dc8bd36,0xbf7ec46d,0xbd48fb30,0xbf7fb10f,0xbe47c5c2,0xbf7b14be,0xbeac7cd4,0xbf710908,0xbef15aea,0xbf61c598,0xbf187fc0,0xbf4d9f02,
0x3eac7cd4,0xbf710908,0x3e419b37,0xbf7b61fc,0x3d16c32c,0xbf7fd397,0xbdee3876,0xbf7e4323,0xbe888e93,0xbf76ba07,0xbed25a09,0xbf696591,0xbf0b9a6b,0xbf5695e5,0xbf2ac082,0xbf3ebc1b,
0x3e94a031,0xbf74fa0b,0x3e09cf86,0xbf7dabcc,0xbcc90ab0,0xbf7fec43,0xbe3b6ecf,0xbf7baccd,0xbeac7cd4,0xbf710908,0xbef6e0cb,0xbf604621,0xbf1d7fd1,0xbf49d112,0xbf3b8f3b,0xbf2e3bde,
0x3e78cfcc,0xbf7853f8,0x3da3308c,0xbf7f2f9d,0xbdafb680,0xbf7f0e58,0xbe7ee6e1,0xbf77f110,0xbecf7bca,0xbf6a09a7,0xbf0cead0,0xbf55b993,0xbf2e3bde,0xbf3b8f3b,0xbf4ac77f,0xbf1c420c,
0x3e47c5c2,0xbf7b14be,0x3cc90ab0,0xbf7fec43,0xbe164083,0xbf7d3aac,0xbea09ae5,0xbf731447,0xbef15aea,0xbf61c598,0xbf1d7fd1,0xbf49d112,0xbf3daef9,0xbf2beb4a,0xbf584853,0xbf08f59b,
0x3e164083,0xbf7d3aac,0xbcfb49ba,0xbf7fe129,0xbe541501,0xbf7a7302,0xbec1071e,0xbf6d1c1d,0xbf08f59b,0xbf584853,0xbf2d1469,0xbf3ca003,0xbf4bbbf8,0xbf1b02c6,0xbf63f473,0xbee900b7,
0x3dc8bd36,0xbf7ec46d,0xbdafb680,0xbf7f0e58,0xbe888e93,0xbf76ba07,0xbee0924f,0xbf660f88,0xbf187fc0,0xbf4d9f02,0xbf3b8f3b,0xbf2e3bde,0xbf584853,0xbf08f59b,0xbf6db293,0xbebe1d4a,
0x3d48fb30,0xbf7fb10f,0xbe1008b7,0xbf7d7474,0xbea68f12,0xbf721352,0xbeff17b2,0xbf5df6be,0xbf273656,0xbf41d870,0xbf48d8b3,0xbf1ebc12,0xbf633c5a,0xbeebcbbb,0xbf756d97,0xbe919ddd,
0x3f800000,0x0,0x3f800000,0x0,0x3f800000,0x0,0x3f800000,0x0,0x3f800000,0x0,0x3f800000,0x0,0x3f800000,0x0,0x3f800000,0x0,
0x3f7ec46d,0xbdc8bd36,0x3f7e9bc9,0xbdd53db9,0x3f7e70b0,0xbde1bc2e,0x3f7e4323,0xbdee3876,0x3f7e1324,0xbdfab273,0x3f7de0b1,0xbe039502,0x3f7dabcc,0xbe09cf86,0x3f7d7474,0xbe1008b7,
0x3f7b14be,0xbe47c5c2,0x3f7a7302,0xbe541501,0x3f79c79d,0xbe605c13,0x3f791298,0xbe6c9a7f,0x3f7853f8,0xbe78cfcc,0x3f778bc5,0xbe827dc0,0x3f76ba07,0xbe888e93,0x3f75dec6,0xbe8e9a22,
0x3f74fa0b,0xbe94a031,0x3f73913f,0xbe9d9e78,0x3f721352,0xbea68f12,0x3f708066,0xbeaf713a,0x3f6ed89e,0xbeb8442a,0x3f6d1c1d,0xbec1071e,0x3f6b4b0c,0xbec9b953,0x3f696591,0xbed25a09,
0x3f6c835e,0xbec3ef15,0x3f6a09a7,0xbecf7bca,0x3f676bd8,0xbedae880,0x3f64aa59,0xbee63375,0x3f61c598,0xbef15aea,0x3f5ebe05,0xbefc5d27,0x3f5b941a,0xbf039c3d,0x3f584853,0xbf08f59b,
0x3f61c598,0xbef15aea,0x3f5df6be,0xbeff17b2,0x3f59f26a,0xbf064b82,0x3f55b993,0xbf0cead0,0x3f514d3d,0xbf13682a,0x3f4cae79,0xbf19c200,0x3f47de65,0xbf1ff6cb,0x3f42de29,0xbf26050a,
0x3f54db31,0xbf0e39da,0x3f4f7a1f,0xbf15f6d9,0x3f49d112,0xbf1d7fd1,0x3f43e200,0xbf24d225,0x3f3daef9,0xbf2beb4a,0x3f373a23,0xbf32c8c9,0x3f3085bb,0xbf396842,0x3f299415,0xbf3fc767,
0x3f45e403,0xbf226799,0x3f3ebc1b,0xbf2ac082,0x3f373a23,0xbf32c8c9,0x3f2f61a5,0xbf3a7ca4,0x3f273656,0xbf41d870,0x3f1ebc12,0xbf48d8b3,0x3f15f6d9,0xbf4f7a1f,0x3f0cead0,0xbf55b993,
0x3f3504f3,0xbf3504f3,0x3f2beb4a,0xbf3daef9,0x3f226799,0xbf45e403,0x3f187fc0,0xbf4d9f02,0x3f0e39da,0xbf54db31,0x3f039c3d,0xbf5b941a,0x3ef15aea,0xbf61c598,0x3edae880,0xbf676bd8,
0x3f226799,0xbf45e403,0x3f173c07,0xbf4e8d90,0x3f0b9a6b,0xbf5695e5,0x3eff17b2,0xbf5df6be,0x3ee63375,0xbf64aa59,0x3ecc9b8b,0xbf6aab7b,0x3eb263ef,0xbf6ff573,0x3e97a117,0xbf748422,
0x3f0e39da,0xbf54db31,0x3f00e7e4,0xbf5d2d53,0x3ee63375,0xbf64aa59,0x3ec9b953,0xbf6b4b0c,0x3eac7cd4,0xbf710908,0x3e8e9a22,0xbf75dec6,0x3e605c13,0xbf79c79d,0x3e22abb6,0xbf7cbfc9,
0x3ef15aea,0xbf61c598,0x3ed25a09,0xbf696591,0x3eb263ef,0xbf6ff573,0x3e919ddd,0xbf756d97,0x3e605c13,0xbf79c79d,0x3e1c76de,0xbf7cfe73,0x3dafb680,0xbf7f0e58,0x3c96c9b6,0xbf7ff4e6,
0x3ec3ef15,0xbf6c835e,0x3ea09ae5,0xbf731447,0x3e78cfcc,0xbf7853f8,0x3e2f10a2,0xbf7c3b28,0x3dc8bd36,0xbf7ec46d,0x3cc90ab0,0xbf7fec43,0xbd48fb30,0xbf7fb10f,0xbdfab273,0xbf7e1324,
0x3e94a031,0xbf74fa0b,0x3e5a3997,0xbf7a1e84,0x3e09cf86,0xbf7dabcc,0x3d621469,0xbf7f9c18,0xbcc90ab0,0xbf7fec43,0xbdd53db9,0xbf7e9bc9,0xbe3b6ecf,0xbf7baccd,0xbe8586ce,0xbf772417,
0x3e47c5c2,0xbf7b14be,0x3de1bc2e,0xbf7e70b0,0x3cc90ab0,0xbf7fec43,0xbd7b2b74,0xbf7f84ab,0xbe164083,0xbf7d3aac,0xbe6c9a7f,0xbf791298,0xbea09ae5,0xbf731447,0xbec9b953,0xbf6b4b0c,
0x3dc8bd36,0xbf7ec46d,0x3bc90f88,0xbf7ffec4,0xbdafb680,0xbf7f0e58,0xbe354098,0xbf7bf531,0xbe888e93,0xbf76ba07,0xbeb554ec,0xbf6f6830,0xbee0924f,0xbf660f88,0xbf04f484,0xbf5ac450,
0x0,0xbf800000,0xbdc8bd36,0xbf7ec46d,0xbe47c5c2,0xbf7b14be,0xbe94a031,0xbf74fa0b,0xbec3ef15,0xbf6c835e,0xbef15aea,0xbf61c598,0xbf0e39da,0xbf54db31,0xbf226799,0xbf45e403,
0xbdc8bd36,0xbf7ec46d,0xbe4dee60,0xbf7ac516,0xbe9aa086,0xbf740bdd,0xbecc9b8b,0xbf6aab7b,0xbefc5d27,0xbf5ebe05,0xbf14b039,0xbf5064af,0xbf299415,0xbf3fc767,0xbf3ca003,0xbf2d1469,
0xbe47c5c2,0xbf7b14be,0xbe9aa086,0xbf740bdd,0xbecf7bca,0xbf6a09a7,0xbf00e7e4,0xbf5d2d53,0xbf187fc0,0xbf4d9f02,0xbf2e3bde,0xbf3b8f3b,0xbf41d870,0xbf273656,0xbf531849,0xbf10d3cd,
0xbe94a031,0xbf74fa0b,0xbecc9b8b,0xbf6aab7b,0xbf00e7e4,0xbf5d2d53,0xbf19c200,0xbf4cae79,0xbf3085bb,0xbf396842,0xbf44e3f5,0xbf239da9,0xbf5695e5,0xbf0b9a6b,0xbf655e0b,0xbee363fa,
0xbec3ef15,0xbf6c835e,0xbefc5d27,0xbf5ebe05,0xbf187fc0,0xbf4d9f02,0xbf3085bb,0xbf396842,0xbf45e403,0xbf226799,0xbf584853,0xbf08f59b,0xbf676bd8,0xbedae880,0xbf731447,0xbea09ae5,
0xbef15aea,0xbf61c598,0xbf14b039,0xbf5064af,0xbf2e3bde,0xbf3b8f3b,0xbf44e3f5,0xbf239da9,0xbf584853,0xbf08f59b,0xbf6816a8,0xbed8106b,0xbf740bdd,0xbe9aa086,0xbf7bf531,0xbe354098,
0xbf0e39da,0xbf54db31,0xbf299415,0xbf3fc767,0xbf41d870,0xbf273656,0xbf5695e5,0xbf0b9a6b,0xbf676bd8,0xbedae880,0xbf740bdd,0xbe9aa086,0xbf7c3b28,0xbe2f10a2,0xbf7fd397,0xbd16c32c,
0xbf226799,0xbf45e403,0xbf3ca003,0xbf2d1469,0xbf531849,0xbf10d3cd,0xbf655e0b,0xbee363fa,0xbf731447,0xbea09ae5,0xbf7bf531,0xbe354098,0xbf7fd397,0xbd16c32c,0xbf7e9bc9,0x3dd53db9,
0xbf3504f3,0xbf3504f3,0xbf4d9f02,0xbf187fc0,0xbf61c598,0xbef15aea,0xbf710908,0xbeac7cd4,0xbf7b14be,0xbe47c5c2,0xbf7fb10f,0xbd48fb30,0xbf7ec46d,0x3dc8bd36,0xbf7853f8,0x3e78cfcc,
0xbf45e403,0xbf226799,0xbf5c61c7,0xbf0242b1,0xbf6db293,0xbebe1d4a,0xbf796e4e,0xbe667c66,0xbf7f4e6d,0xbd96a905,0xbf7f2f9d,0x3da3308c,0xbf791298,0x3e6c9a7f,0xbf6d1c1d,0x3ec1071e,
0xbf54db31,0xbf0e39da,0xbf68bf3c,0xbed53641,0xbf76ba07,0xbe888e93,0xbf7e70b0,0xbde1bc2e,0xbf7fb10f,0x3d48fb30,0xbf7a7302,0x3e541501,0xbf6ed89e,0x3eb8442a,0xbf5d2d53,0x3f00e7e4,
0xbf61c598,0xbef15aea,0xbf7294f8,0xbea395c5,0xbf7cbfc9,0xbe22abb6,0xbf7ffec4,0x3bc90f88,0xbf7c3b28,0x3e2f10a2,0xbf718f57,0x3ea986c4,0xbf604621,0x3ef6e0cb,0xbf48d8b3,0x3f1ebc12,
0xbf6c835e,0xbec3ef15,0xbf79c79d,0xbe605c13,0xbf7fb10f,0xbd48fb30,0xbf7e1324,0x3dfab273,0xbf74fa0b,0x3e94a031,0xbf64aa59,0x3ee63375,0xbf4d9f02,0x3f187fc0,0xbf3085bb,0x3f396842,
0xbf74fa0b,0xbe94a031,0xbf7e4323,0xbdee3876,0xbf7f84ab,0x3d7b2b74,0xbf78b47b,0x3e72b651,0xbf6a09a7,0x3ecf7bca,0xbf53fac3,0x3f0f8784,0xbf373a23,0x3f32c8c9,0xbf14b039,0x3f5064af,
0xbf7b14be,0xbe47c5c2,0xbf7ffb11,0xbc490e90,0xbf7c3b28,0x3e2f10a2,0xbf6ff573,0x3eb263ef,0xbf5b941a,0x3f039c3d,0xbf3fc767,0x3f299415,0xbf1d7fd1,0x3f49d112,0xbeebcbbb,0x3f633c5a,
0xbf7ec46d,0xbdc8bd36,0xbf7eea9d,0x3dbc3ac3,0xbf75dec6,0x3e8e9a22,0xbf63f473,0x3ee900b7,0xbf49d112,0x3f1d7fd1,0xbf286605,0x3f40d0da,0xbf00e7e4,0x3f5d2d53,0xbea986c4,0x3f718f57,
0x3f800000,0x0,0x3f800000,0x0,0x3f800000,0x0,0x3f800000,0x0,0x3f800000,0x0,0x3f800000,0x0,0x3f800000,0x0,0x3f800000,0x0,
0x3f7d3aac,0xbe164083,0x3f7cfe73,0xbe1c76de,0x3f7cbfc9,0xbe22abb6,0x3f7c7eb0,0xbe28defc,0x3f7c3b28,0xbe2f10a2,0x3f7bf531,0xbe354098,0x3f7baccd,0xbe3b6ecf,0x3f7b61fc,0xbe419b37,
0x3f74fa0b,0xbe94a031,0x3f740bdd,0xbe9aa086,0x3f731447,0xbea09ae5,0x3f721352,0xbea68f12,0x3f710908,0xbeac7cd4,0x3f6ff573,0xbeb263ef,0x3f6ed89e,0xbeb8442a,0x3f6db293,0xbebe1d4a,
0x3f676bd8,0xbedae880,0x3f655e0b,0xbee363fa,0x3f633c5a,0xbeebcbbb,0x3f6106f2,0xbef41f07,0x3f5ebe05,0xbefc5d27,0x3f5c61c7,0xbf0242b1,0x3f59f26a,0xbf064b82,0x3f577026,0xbf0a48ad,
0x3f54db31,0xbf0e39da,0x3f514d3d,0xbf13682a,0x3f4d9f02,0xbf187fc0,0x3f49d112,0xbf1d7fd1,0x3f45e403,0xbf226799,0x3f41d870,0xbf273656,0x3f3daef9,0xbf2beb4a,0x3f396842,0xbf3085bb,
0x3f3daef9,0xbf2beb4a,0x3f385216,0xbf31a81d,0x3f32c8c9,0xbf373a23,0x3f2d1469,0xbf3ca003,0x3f273656,0xbf41d870,0x3f212ff9,0xbf46e22a,0x3f1b02c6,0xbf4bbbf8,0x3f14b039,0xbf5064af,
0x3f226799,0xbf45e403,0x3f1b02c6,0xbf4bbbf8,0x3f13682a,0xbf514d3d,0x3f0b9a6b,0xbf5695e5,0x3f039c3d,0xbf5b941a,0x3ef6e0cb,0xbf604621,0x3ee63375,0xbf64aa59,0x3ed53641,0xbf68bf3c,
0x3f039c3d,0xbf5b941a,0x3ef41f07,0xbf6106f2,0x3ee0924f,0xbf660f88,0x3ecc9b8b,0xbf6aab7b,0x3eb8442a,0xbf6ed89e,0x3ea395c5,0xbf7294f8,0x3e8e9a22,0xbf75dec6,0x3e72b651,0xbf78b47b,
0x3ec3ef15,0xbf6c835e,0x3eac7cd4,0xbf710908,0x3e94a031,0xbf74fa0b,0x3e78cfcc,0xbf7853f8,0x3e47c5c2,0xbf7b14be,0x3e164083,0xbf7d3aac,0x3dc8bd36,0xbf7ec46d,0x3d48fb30,0xbf7fb10f,
0x3e78cfcc,0xbf7853f8,0x3e419b37,0xbf7b61fc,0x3e09cf86,0xbf7dabcc,0x3da3308c,0xbf7f2f9d,0x3cc90ab0,0xbf7fec43,0xbcfb49ba,0xbf7fe129,0xbdafb680,0xbf7f0e58,0xbe1008b7,0xbf7d7474,
0x3dc8bd36,0xbf7ec46d,0x3d16c32c,0xbf7fd397,0xbcc90ab0,0xbf7fec43,0xbdafb680,0xbf7f0e58,0xbe164083,0xbf7d3aac,0xbe541501,0xbf7a7302,0xbe888e93,0xbf76ba07,0xbea68f12,0xbf721352,
0xbd48fb30,0xbf7fb10f,0xbdee3876,0xbf7e4323,0xbe3b6ecf,0xbf7baccd,0xbe7ee6e1,0xbf77f110,0xbea09ae5,0xbf731447,0xbec1071e,0xbf6d1c1d,0xbee0924f,0xbf660f88,0xbeff17b2,0xbf5df6be,
0xbe47c5c2,0xbf7b14be,0xbe888e93,0xbf76ba07,0xbeac7cd4,0xbf710908,0xbecf7bca,0xbf6a09a7,0xbef15aea,0xbf61c598,0xbf08f59b,0xbf584853,0xbf187fc0,0xbf4d9f02,0xbf273656,0xbf41d870,
0xbeac7cd4,0xbf710908,0xbed25a09,0xbf696591,0xbef6e0cb,0xbf604621,0xbf0cead0,0xbf55b993,0xbf1d7fd1,0xbf49d112,0xbf2d1469,0xbf3ca003,0xbf3b8f3b,0xbf2e3bde,0xbf48d8b3,0xbf1ebc12,
0xbef15aea,0xbf61c598,0xbf0b9a6b,0xbf5695e5,0xbf1d7fd1,0xbf49d112,0xbf2e3bde,0xbf3b8f3b,0xbf3daef9,0xbf2beb4a,0xbf4bbbf8,0xbf1b02c6,0xbf584853,0xbf08f59b,0xbf633c5a,0xbeebcbbb,
0xbf187fc0,0xbf4d9f02,0xbf2ac082,0xbf3ebc1b,0xbf3b8f3b,0xbf2e3bde,0xbf4ac77f,0xbf1c420c,0xbf584853,0xbf08f59b,0xbf63f473,0xbee900b7,0xbf6db293,0xbebe1d4a,0xbf756d97,0xbe919ddd,
0xbf3504f3,0xbf3504f3,0xbf45e403,0xbf226799,0xbf54db31,0xbf0e39da,0xbf61c598,0xbef15aea,0xbf6c835e,0xbec3ef15,0xbf74fa0b,0xbe94a031,0xbf7b14be,0xbe47c5c2,0xbf7ec46d,0xbdc8bd36,
0xbf4d9f02,0xbf187fc0,0xbf5c61c7,0xbf0242b1,0xbf68bf3c,0xbed53641,0xbf7294f8,0xbea395c5,0xbf79c79d,0xbe605c13,0xbf7e4323,0xbdee3876,0xbf7ffb11,0xbc490e90,0xbf7eea9d,0x3dbc3ac3,
0xbf61c598,0xbef15aea,0xbf6db293,0xbebe1d4a,0xbf76ba07,0xbe888e93,0xbf7cbfc9,0xbe22abb6,0xbf7fb10f,0xbd48fb30,0xbf7f84ab,0x3d7b2b74,0xbf7c3b28,0x3e2f10a2,0xbf75dec6,0x3e8e9a22,
0xbf710908,0xbeac7cd4,0xbf796e4e,0xbe667c66,0xbf7e70b0,0xbde1bc2e,0xbf7ffec4,0x3bc90f88,0xbf7e1324,0x3dfab273,0xbf78b47b,0x3e72b651,0xbf6ff573,0x3eb263ef,0xbf63f473,0x3ee900b7,
0xbf7b14be,0xbe47c5c2,0xbf7f4e6d,0xbd96a905,0xbf7fb10f,0x3d48fb30,0xbf7c3b28,0x3e2f10a2,0xbf74fa0b,0x3e94a031,0xbf6a09a7,0x3ecf7bca,0xbf5b941a,0x3f039c3d,0xbf49d112,0x3f1d7fd1,
0xbf7fb10f,0xbd48fb30,0xbf7f2f9d,0x3da3308c,0xbf7a7302,0x3e541501,0xbf718f57,0x3ea986c4,0xbf64aa59,0x3ee63375,0xbf53fac3,0x3f0f8784,0xbf3fc767,0x3f299415,0xbf286605,0x3f40d0da,
0xbf7ec46d,0x3dc8bd36,0xbf791298,0x3e6c9a7f,0xbf6ed89e,0x3eb8442a,0xbf604621,0x3ef6e0cb,0xbf4d9f02,0x3f187fc0,0xbf373a23,0x3f32c8c9,0xbf1d7fd1,0x3f49d112,0xbf00e7e4,0x3f5d2d53,
0xbf7853f8,0x3e78cfcc,0xbf6d1c1d,0x3ec1071e,0xbf5d2d53,0x3f00e7e4,0xbf48d8b3,0x3f1ebc12,0xbf3085bb,0x3f396842,0xbf14b039,0x3f5064af,0xbeebcbbb,0x3f633c5a,0xbea986c4,0x3f718f57,
0xbf6c835e,0x3ec3ef15,0xbf5b941a,0x3f039c3d,0xbf45e403,0x3f226799,0xbf2beb4a,0x3f3daef9,0xbf0e39da,0x3f54db31,0xbedae880,0x3f676bd8,0xbe94a031,0x3f74fa0b,0xbe164083,0x3f7d3aac,
0xbf5b941a,0x3f039c3d,0xbf44e3f5,0x3f239da9,0xbf299415,0x3f3fc767,0xbf0a48ad,0x3f577026,0xbecf7bca,0x3f6a09a7,0xbe8586ce,0x3f772417,0xbde1bc2e,0x3f7e70b0,0x3d2fe007,0x3f7fc38f,
0xbf45e403,0x3f226799,0xbf299415,0x3f3fc767,0xbf08f59b,0x3f584853,0xbec9b953,0x3f6b4b0c,0xbe78cfcc,0x3f7853f8,0xbdafb680,0x3f7f0e58,0x3d96a905,0x3f7f4e6d,0x3e6c9a7f,0x3f791298,
0xbf2beb4a,0x3f3daef9,0xbf0a48ad,0x3f577026,0xbec9b953,0x3f6b4b0c,0xbe72b651,0x3f78b47b,0xbd96a905,0x3f7f4e6d,0x3dbc3ac3,0x3f7eea9d,0x3e827dc0,0x3f778bc5,0x3ed25a09,0x3f696591,
0xbf0e39da,0x3f54db31,0xbecf7bca,0x3f6a09a7,0xbe78cfcc,0x3f7853f8,0xbd96a905,0x3f7f4e6d,0x3dc8bd36,0x3f7ec46d,0x3e888e93,0x3f76ba07,0x3edae880,0x3f676bd8,0x3f13682a,0x3f514d3d,
0xbedae880,0x3f676bd8,0xbe8586ce,0x3f772417,0xbdafb680,0x3f7f0e58,0x3dbc3ac3,0x3f7eea9d,0x3e888e93,0x3f76ba07,0x3eddbe79,0x3f66becc,0x3f15f6d9,0x3f4f7a1f,0x3f385216,0x3f31a81d,
0xbe94a031,0x3f74fa0b,0xbde1bc2e,0x3f7e70b0,0x3d96a905,0x3f7f4e6d,0x3e827dc0,0x3f778bc5,0x3edae880,0x3f676bd8,0x3f15f6d9,0x3f4f7a1f,0x3f396842,0x3f3085bb,0x3f5695e5,0x3f0b9a6b,
0xbe164083,0x3f7d3aac,0x3d2fe007,0x3f7fc38f,0x3e6c9a7f,0x3f791298,0x3ed25a09,0x3f696591,0x3f13682a,0x3f514d3d,0x3f385216,0x3f31a81d,0x3f5695e5,0x3f0b9a6b,0x3f6d1c1d,0x3ec1071e,
0xbd803d80,0x80003e00,0x80003e00,0x80003e00,0x80003e00,0x80003e00,0x80003e00,0x80003e00,0x80003e00,0x80003e00,0x80003e00,0x80003e00,0x80003e00,0x80003e00,0x80003e00,0x80003e00,
0x3d803d80,0x3cc83dfb,0x3e000000,0x3dfbbcc8,0x3d443ded,0x3d8e3dd5,0x3dedbd44,0x3dd5bd8e,0x3db53db5,0x3dd53d8e,0x3db5bdb5,0x3d8ebdd5,0x3ded3d44,0x3dfb3cc8,0x3d44bded,0x3cc8bdfb,
0xbd803d80,0x3d443ded,0x8000be00,0xbd44bded,0x3db53db5,0x3ded3d44,0xbdb5bdb5,0xbdedbd44,0x3e000000,0x3dedbd44,0xbe000000,0xbded3d44,0x3db5bdb5,0x3d44bded,0xbdb53db5,0xbd443ded,
0x3d803d80,0x3d8e3dd5,0xbe000000,0xbdd53d8e,0x3ded3d44,0x3dfbbcc8,0xbd443ded,0x3cc83dfb,0x3db5bdb5,0x3cc8bdfb,0x3db53db5,0x3dfb3cc8,0xbd44bded,0xbdd5bd8e,0x3dedbd44,0x3d8ebdd5,
0xbd803d80,0x3db53db5,0x80003e00,0x3db53db5,0x3e000000,0x3db5bdb5,0x3e000000,0x3db5bdb5,0x8000be00,0xbdb5bdb5,0x8000be00,0xbdb5bdb5,0xbe000000,0xbdb53db5,0xbe000000,0xbdb53db5,
0x3d803d80,0x3dd53d8e,0x3e000000,0x3d8ebdd5,0x3dedbd44,0x3cc8bdfb,0xbd44bded,0xbdfbbcc8,0xbdb5bdb5,0xbdfb3cc8,0xbdb53db5,0x3cc83dfb,0xbd443ded,0x3d8e3dd5,0x3ded3d44,0x3dd5bd8e,
0xbd803d80,0x3ded3d44,0x8000be00,0xbdedbd44,0x3db5bdb5,0xbd44bded,0xbdb53db5,0x3d443ded,0xbe000000,0xbd443ded,0x3e000000,0x3d44bded,0x3db53db5,0x3dedbd44,0xbdb5bdb5,0xbded3d44,
0x3d803d80,0x3dfb3cc8,0xbe000000,0xbcc83dfb,0x3d44bded,0xbdd5bd8e,0x3ded3d44,0x3d8ebdd5,0xbdb53db5,0x3d8e3dd5,0xbdb5bdb5,0xbdd53d8e,0x3dedbd44,0xbcc8bdfb,0x3d443ded,0x3dfbbcc8,
0xbd803d80,0x3e000000,0x80003e00,0x3e000000,0x8000be00,0xbe000000,0x8000be00,0xbe000000,0x80003e00,0x3e000000,0x80003e00,0x3e000000,0x8000be00,0xbe000000,0x8000be00,0xbe000000,
0x3d803d80,0x3dfbbcc8,0x3e000000,0xbcc8bdfb,0xbd44bded,0xbdd53d8e,0xbded3d44,0x3d8e3dd5,0x3db53db5,0x3d8ebdd5,0x3db5bdb5,0xbdd5bd8e,0xbdedbd44,0xbcc83dfb,0xbd443ded,0x3dfb3cc8,
0xbd803d80,0x3dedbd44,0x8000be00,0xbded3d44,0xbdb5bdb5,0xbd443ded,0x3db53db5,0x3d44bded,0x3e000000,0xbd44bded,0xbe000000,0x3d443ded,0xbdb53db5,0x3ded3d44,0x3db5bdb5,0xbdedbd44,
0x3d803d80,0x3dd5bd8e,0xbe000000,0x3d8e3dd5,0xbdedbd44,0x3cc83dfb,0x3d44bded,0xbdfb3cc8,0x3db5bdb5,0xbdfbbcc8,0x3db53db5,0x3cc8bdfb,0x3d443ded,0x3d8ebdd5,0xbded3d44,0x3dd53d8e,
0xbd803d80,0x3db5bdb5,0x80003e00,0x3db5bdb5,0xbe000000,0x3db53db5,0xbe000000,0x3db53db5,0x8000be00,0xbdb53db5,0x8000be00,0xbdb53db5,0x3e000000,0xbdb5bdb5,0x3e000000,0xbdb5bdb5,
0x3d803d80,0x3d8ebdd5,0x3e000000,0xbdd5bd8e,0xbded3d44,0x3dfb3cc8,0x3d443ded,0x3cc8bdfb,0xbdb5bdb5,0x3cc83dfb,0xbdb53db5,0x3dfbbcc8,0x3d44bded,0xbdd53d8e,0xbdedbd44,0x3d8e3dd5,
0xbd803d80,0x3d44bded,0x8000be00,0xbd443ded,0xbdb53db5,0x3dedbd44,0x3db5bdb5,0xbded3d44,0xbe000000,0x3ded3d44,0x3e000000,0xbdedbd44,0xbdb5bdb5,0x3d443ded,0x3db53db5,0xbd44bded,
0x3d803d80,0x3cc8bdfb,0xbe000000,0x3dfb3cc8,0xbd443ded,0x3d8ebdd5,0xbdedbd44,0x3dd53d8e,0xbdb53db5,0x3dd5bd8e,0xbdb5bdb5,0x3d8e3dd5,0xbded3d44,0x3dfbbcc8,0xbd44bded,0x3cc83dfb,
0xbd803d80,0x8000be00,0x80003e00,0x8000be00,0x80003e00,0x8000be00,0x80003e00,0x8000be00,0x80003e00,0x8000be00,0x80003e00,0x8000be00,0x80003e00,0x8000be00,0x80003e00,0x8000be00,
0x3d803d80,0xbcc8bdfb,0x3e000000,0xbdfb3cc8,0x3d443ded,0xbd8ebdd5,0x3dedbd44,0xbdd53d8e,0x3db53db5,0xbdd5bd8e,0x3db5bdb5,0xbd8e3dd5,0x3ded3d44,0xbdfbbcc8,0x3d44bded,0xbcc83dfb,
0xbd803d80,0xbd44bded,0x8000be00,0x3d443ded,0x3db53db5,0xbdedbd44,0xbdb5bdb5,0x3ded3d44,0x3e000000,0xbded3d44,0xbe000000,0x3dedbd44,0x3db5bdb5,0xbd443ded,0xbdb53db5,0x3d44bded,
0x3d803d80,0xbd8ebdd5,0xbe000000,0x3dd5bd8e,0x3ded3d44,0xbdfb3cc8,0xbd443ded,0xbcc8bdfb,0x3db5bdb5,0xbcc83dfb,0x3db53db5,0xbdfbbcc8,0xbd44bded,0x3dd53d8e,0x3dedbd44,0xbd8e3dd5,
0xbd803d80,0xbdb5bdb5,0x80003e00,0xbdb5bdb5,0x3e000000,0xbdb53db5,0x3e000000,0xbdb53db5,0x8000be00,0x3db53db5,0x8000be00,0x3db53db5,0xbe000000,0x3db5bdb5,0xbe000000,0x3db5bdb5,
0x3d803d80,0xbdd5bd8e,0x3e000000,0xbd8e3dd5,0x3dedbd44,0xbcc83dfb,0xbd44bded,0x3dfb3cc8,0xbdb5bdb5,0x3dfbbcc8,0xbdb53db5,0xbcc8bdfb,0xbd443ded,0xbd8ebdd5,0x3ded3d44,0xbdd53d8e,
0xbd803d80,0xbdedbd44,0x8000be00,0x3ded3d44,0x3db5bdb5,0x3d443ded,0xbdb53db5,0xbd44bded,0xbe000000,0x3d44bded,0x3e000000,0xbd443ded,0x3db53db5,0xbded3d44,0xbdb5bdb5,0x3dedbd44,
0x3d803d80,0xbdfbbcc8,0xbe000000,0x3cc8bdfb,0x3d44bded,0x3dd53d8e,0x3ded3d44,0xbd8e3dd5,0xbdb53db5,0xbd8ebdd5,0xbdb5bdb5,0x3dd5bd8e,0x3dedbd44,0x3cc83dfb,0x3d443ded,0xbdfb3cc8,
0xbd803d80,0xbe000000,0x80003e00,0xbe000000,0x8000be00,0x3e000000,0x8000be00,0x3e000000,0x80003e00,0xbe000000,0x80003e00,0xbe000000,0x8000be00,0x3e000000,0x8000be00,0x3e000000,
0x3d803d80,0xbdfb3cc8,0x3e000000,0x3cc83dfb,0xbd44bded,0x3dd5bd8e,0xbded3d44,0xbd8ebdd5,0x3db53db5,0xbd8e3dd5,0x3db5bdb5,0x3dd53d8e,0xbdedbd44,0x3cc8bdfb,0xbd443ded,0xbdfbbcc8,
0xbd803d80,0xbded3d44,0x8000be00,0x3dedbd44,0xbdb5bdb5,0x3d44bded,0x3db53db5,0xbd443ded,0x3e000000,0x3d443ded,0xbe000000,0xbd44bded,0xbdb53db5,0xbdedbd44,0x3db5bdb5,0x3ded3d44,
0x3d803d80,0xbdd53d8e,0xbe000000,0xbd8ebdd5,0xbdedbd44,0xbcc8bdfb,0x3d44bded,0x3dfbbcc8,0x3db5bdb5,0x3dfb3cc8,0x3db53db5,0xbcc83dfb,0x3d443ded,0xbd8e3dd5,0xbded3d44,0xbdd5bd8e,
0xbd803d80,0xbdb53db5,0x80003e00,0xbdb53db5,0xbe000000,0xbdb5bdb5,0xbe000000,0xbdb5bdb5,0x8000be00,0x3db5bdb5,0x8000be00,0x3db5bdb5,0x3e000000,0x3db53db5,0x3e000000,0x3db53db5,
0x3d803d80,0xbd8e3dd5,0x3e000000,0x3dd53d8e,0xbded3d44,0xbdfbbcc8,0x3d443ded,0xbcc83dfb,0xbdb5bdb5,0xbcc8bdfb,0xbdb53db5,0xbdfb3cc8,0x3d44bded,0x3dd5bd8e,0xbdedbd44,0xbd8ebdd5,
0xbd803d80,0xbd443ded,0x8000be00,0x3d44bded,0xbdb53db5,0xbded3d44,0x3db5bdb5,0x3dedbd44,0xbe000000,0xbdedbd44,0x3e000000,0x3ded3d44,0xbdb5bdb5,0xbd44bded,0x3db53db5,0x3d443ded,
0x3d803d80,0xbcc83dfb,0xbe000000,0xbdfbbcc8,0xbd443ded,0xbd8e3dd5,0xbdedbd44,0xbdd5bd8e,0xbdb53db5,0xbdd53d8e,0xbdb5bdb5,0xbd8ebdd5,0xbded3d44,0xbdfb3cc8,0xbd44bded,0xbcc8bdfb,
0x80003e00,0x80003e00,0x80003e00,0x80003e00,0x80003e00,0x80003e00,0x80003e00,0x80003e00,0x80003e00,0x80003e00,0x80003e00,0x80003e00,0x80003e00,0x80003e00,0x80003e00,0x80003e00,
0x3c493dff,0x3d153df5,0x3dffbc49,0x3df5bd15,0x3d713de2,0x3da23dc6,0x3de2bd71,0x3dc6bda2,0x3dc63da2,0x3de23d71,0x3da2bdc6,0x3d71bde2,0x3df53d15,0x3dff3c49,0x3d15bdf5,0x3c49bdff,
0x3cc83dfb,0x3d8e3dd5,0xbcc8bdfb,0xbd8ebdd5,0x3dd53d8e,0x3dfb3cc8,0xbdd5bd8e,0xbdfbbcc8,0x3dfbbcc8,0x3dd5bd8e,0xbdfb3cc8,0xbdd53d8e,0x3d8ebdd5,0x3cc8bdfb,0xbd8e3dd5,0xbcc83dfb,
0x3d153df5,0x3dc63da2,0xbdf53d15,0xbda23dc6,0x3dff3c49,0x3de2bd71,0xbc493dff,0x3d713de2,0x3d71bde2,0xbc49bdff,0x3de23d71,0x3dffbc49,0xbda2bdc6,0xbdf5bd15,0x3dc6bda2,0x3d15bdf5,
0x3d443ded,0x3ded3d44,0x3d443ded,0x3ded3d44,0x3dedbd44,0x3d44bded,0x3dedbd44,0x3d44bded,0xbd44bded,0xbdedbd44,0xbd44bded,0xbdedbd44,0xbded3d44,0xbd443ded,0xbded3d44,0xbd443ded,
0x3d713de2,0x3dff3c49,0x3de2bd71,0x3c49bdff,0x3da2bdc6,0xbd15bdf5,0xbdc6bda2,0xbdf53d15,0xbdf5bd15,0xbdc63da2,0xbd153df5,0x3da23dc6,0x3c493dff,0x3de23d71,0x3dffbc49,0x3d71bde2,
0x3d8e3dd5,0x3dfbbcc8,0xbd8ebdd5,0xbdfb3cc8,0x3cc8bdfb,0xbdd5bd8e,0xbcc83dfb,0x3dd53d8e,0xbdd53d8e,0x3cc83dfb,0x3dd5bd8e,0xbcc8bdfb,0x3dfb3cc8,0x3d8ebdd5,0xbdfbbcc8,0xbd8e3dd5,
0x3da23dc6,0x3de2bd71,0xbdc63da2,0x3d713de2,0xbd15bdf5,0xbdff3c49,0x3df5bd15,0xbc49bdff,0xbc493dff,0x3df53d15,0xbdffbc49,0xbd153df5,0x3d71bde2,0xbdc6bda2,0x3de23d71,0x3da2bdc6,
0x3db53db5,0x3db5bdb5,0x3db53db5,0x3db5bdb5,0xbdb5bdb5,0xbdb53db5,0xbdb5bdb5,0xbdb53db5,0x3db53db5,0x3db5bdb5,0x3db53db5,0x3db5bdb5,0xbdb5bdb5,0xbdb53db5,0xbdb5bdb5,0xbdb53db5,
0x3dc63da2,0x3d71bde2,0x3da2bdc6,0xbde2bd71,0xbdf5bd15,0xbc493dff,0xbd153df5,0x3dff3c49,0x3dffbc49,0xbd15bdf5,0xbc49bdff,0xbdf53d15,0xbde23d71,0x3da23dc6,0x3d713de2,0x3dc6bda2,
0x3dd53d8e,0x3cc8bdfb,0xbdd5bd8e,0xbcc83dfb,0xbdfb3cc8,0x3d8e3dd5,0x3dfbbcc8,0xbd8ebdd5,0x3d8ebdd5,0xbdfbbcc8,0xbd8e3dd5,0x3dfb3cc8,0x3cc83dfb,0x3dd5bd8e,0xbcc8bdfb,0xbdd53d8e,
0x3de23d71,0xbc49bdff,0xbd713de2,0x3dffbc49,0xbdc63da2,0x3df53d15,0xbda2bdc6,0xbd153df5,0xbd15bdf5,0xbda23dc6,0x3df5bd15,0xbdc6bda2,0x3dff3c49,0xbd71bde2,0xbc493dff,0x3de2bd71,
0x3ded3d44,0xbd44bded,0x3ded3d44,0xbd44bded,0xbd443ded,0x3dedbd44,0xbd443ded,0x3dedbd44,0xbdedbd44,0x3d443ded,0xbdedbd44,0x3d443ded,0x3d44bded,0xbded3d44,0x3d44bded,0xbded3d44,
0x3df53d15,0xbda2bdc6,0x3d15bdf5,0xbdc63da2,0x3c493dff,0x3d71bde2,0x3dffbc49,0xbde2bd71,0xbde23d71,0x3dff3c49,0x3d713de2,0x3c49bdff,0xbdc6bda2,0x3d153df5,0xbda23dc6,0x3df5bd15,
0x3dfb3cc8,0xbdd5bd8e,0xbdfbbcc8,0x3dd53d8e,0x3d8e3dd5,0xbcc8bdfb,0xbd8ebdd5,0x3cc83dfb,0xbcc83dfb,0x3d8ebdd5,0x3cc8bdfb,0xbd8e3dd5,0xbdd53d8e,0x3dfbbcc8,0x3dd5bd8e,0xbdfb3cc8,
0x3dff3c49,0xbdf5bd15,0xbc493dff,0x3d15bdf5,0x3de23d71,0xbdc6bda2,0xbd713de2,0x3da2bdc6,0x3da23dc6,0xbd71bde2,0xbdc63da2,0x3de2bd71,0x3d153df5,0xbc49bdff,0xbdf53d15,0x3dffbc49,
0x3e000000,0xbe000000,0x3e000000,0xbe000000,0x3e000000,0xbe000000,0x3e000000,0xbe000000,0x3e000000,0xbe000000,0x3e000000,0xbe000000,0x3e000000,0xbe000000,0x3e000000,0xbe000000,
0x3dffbc49,0xbdf53d15,0xbc49bdff,0x3d153df5,0x3de2bd71,0xbdc63da2,0xbd71bde2,0x3da23dc6,0x3da2bdc6,0xbd713de2,0xbdc6bda2,0x3de23d71,0x3d15bdf5,0xbc493dff,0xbdf5bd15,0x3dff3c49,
0x3dfbbcc8,0xbdd53d8e,0xbdfb3cc8,0x3dd5bd8e,0x3d8ebdd5,0xbcc83dfb,0xbd8e3dd5,0x3cc8bdfb,0xbcc8bdfb,0x3d8e3dd5,0x3cc83dfb,0xbd8ebdd5,0xbdd5bd8e,0x3dfb3cc8,0x3dd53d8e,0xbdfbbcc8,
0x3df5bd15,0xbda23dc6,0x3d153df5,0xbdc6bda2,0x3c49bdff,0x3d713de2,0x3dff3c49,0xbde23d71,0xbde2bd71,0x3dffbc49,0x3d71bde2,0x3c493dff,0xbdc63da2,0x3d15bdf5,0xbda2bdc6,0x3df53d15,
0x3dedbd44,0xbd443ded,0x3dedbd44,0xbd443ded,0xbd44bded,0x3ded3d44,0xbd44bded,0x3ded3d44,0xbded3d44,0x3d44bded,0xbded3d44,0x3d44bded,0x3d443ded,0xbdedbd44,0x3d443ded,0xbdedbd44,
0x3de2bd71,0xbc493dff,0xbd71bde2,0x3dff3c49,0xbdc6bda2,0x3df5bd15,0xbda23dc6,0xbd15bdf5,0xbd153df5,0xbda2bdc6,0x3df53d15,0xbdc63da2,0x3dffbc49,0xbd713de2,0xbc49bdff,0x3de23d71,
0x3dd5bd8e,0x3cc83dfb,0xbdd53d8e,0xbcc8bdfb,0xbdfbbcc8,0x3d8ebdd5,0x3dfb3cc8,0xbd8e3dd5,0x3d8e3dd5,0xbdfb3cc8,0xbd8ebdd5,0x3dfbbcc8,0x3cc8bdfb,0x3dd53d8e,0xbcc83dfb,0xbdd5bd8e,
0x3dc6bda2,0x3d713de2,0x3da23dc6,0xbde23d71,0xbdf53d15,0xbc49bdff,0xbd15bdf5,0x3dffbc49,0x3dff3c49,0xbd153df5,0xbc493dff,0xbdf5bd15,0xbde2bd71,0x3da2bdc6,0x3d71bde2,0x3dc63da2,
0x3db5bdb5,0x3db53db5,0x3db5bdb5,0x3db53db5,0xbdb53db5,0xbdb5bdb5,0xbdb53db5,0xbdb5bdb5,0x3db5bdb5,0x3db53db5,0x3db5bdb5,0x3db53db5,0xbdb53db5,0xbdb5bdb5,0xbdb53db5,0xbdb5bdb5,
0x3da2bdc6,0x3de23d71,0xbdc6bda2,0x3d71bde2,0xbd153df5,0xbdffbc49,0x3df53d15,0xbc493dff,0xbc49bdff,0x3df5bd15,0xbdff3c49,0xbd15bdf5,0x3d713de2,0xbdc63da2,0x3de2bd71,0x3da23dc6,
0x3d8ebdd5,0x3dfb3cc8,0xbd8e3dd5,0xbdfbbcc8,0x3cc83dfb,0xbdd53d8e,0xbcc8bdfb,0x3dd5bd8e,0xbdd5bd8e,0x3cc8bdfb,0x3dd53d8e,0xbcc83dfb,0x3dfbbcc8,0x3d8e3dd5,0xbdfb3cc8,0xbd8ebdd5,
0x3d71bde2,0x3dffbc49,0x3de23d71,0x3c493dff,0x3da23dc6,0xbd153df5,0xbdc63da2,0xbdf5bd15,0xbdf53d15,0xbdc6bda2,0xbd15bdf5,0x3da2bdc6,0x3c49bdff,0x3de2bd71,0x3dff3c49,0x3d713de2,
0x3d44bded,0x3dedbd44,0x3d44bded,0x3dedbd44,0x3ded3d44,0x3d443ded,0x3ded3d44,0x3d443ded,0xbd443ded,0xbded3d44,0xbd443ded,0xbded3d44,0xbdedbd44,0xbd44bded,0xbdedbd44,0xbd44bded,
0x3d15bdf5,0x3dc6bda2,0xbdf5bd15,0xbda2bdc6,0x3dffbc49,0x3de23d71,0xbc49bdff,0x3d71bde2,0x3d713de2,0xbc493dff,0x3de2bd71,0x3dff3c49,0xbda23dc6,0xbdf53d15,0x3dc63da2,0x3d153df5,
0x3cc8bdfb,0x3d8ebdd5,0xbcc83dfb,0xbd8e3dd5,0x3dd5bd8e,0x3dfbbcc8,0xbdd53d8e,0xbdfb3cc8,0x3dfb3cc8,0x3dd53d8e,0xbdfbbcc8,0xbdd5bd8e,0x3d8e3dd5,0x3cc83dfb,0xbd8ebdd5,0xbcc8bdfb,
0x3c49bdff,0x3d15bdf5,0x3dff3c49,0x3df53d15,0x3d71bde2,0x3da2bdc6,0x3de23d71,0x3dc63da2,0x3dc6bda2,0x3de2bd71,0x3da23dc6,0x3d713de2,0x3df5bd15,0x3dffbc49,0x3d153df5,0x3c493dff,
0x3f800000,0x0,0x3f800000,0x0,0x3f800000,0x0,0x3f800000,0x0,0x3f800000,0x0,0x3f800000,0x0,0x3f800000,0x0,0x3f800000,0x0,
0x3f800000,0x0,0x3f7ffb11,0xbc490e90,0x3f7fec43,0xbcc90ab0,0x3f7fd397,0xbd16c32c,0x3f7fb10f,0xbd48fb30,0x3f7f84ab,0xbd7b2b74,0x3f7f4e6d,0xbd96a905,0x3f7f0e58,0xbdafb680,
0x3f800000,0x0,0x3f7fec43,0xbcc90ab0,0x3f7fb10f,0xbd48fb30,0x3f7f4e6d,0xbd96a905,0x3f7ec46d,0xbdc8bd36,0x3f7e1324,0xbdfab273,0x3f7d3aac,0xbe164083,0x3f7c3b28,0xbe2f10a2,
0x3f800000,0x0,0x3f7fd397,0xbd16c32c,0x3f7f4e6d,0xbd96a905,0x3f7e70b0,0xbde1bc2e,0x3f7d3aac,0xbe164083,0x3f7baccd,0xbe3b6ecf,0x3f79c79d,0xbe605c13,0x3f778bc5,0xbe827dc0,
0x3f800000,0x0,0x3f7fb10f,0xbd48fb30,0x3f7ec46d,0xbdc8bd36,0x3f7d3aac,0xbe164083,0x3f7b14be,0xbe47c5c2,0x3f7853f8,0xbe78cfcc,0x3f74fa0b,0xbe94a031,0x3f710908,0xbeac7cd4,
0x3f800000,0x0,0x3f7f84ab,0xbd7b2b74,0x3f7e1324,0xbdfab273,0x3f7baccd,0xbe3b6ecf,0x3f7853f8,0xbe78cfcc,0x3f740bdd,0xbe9aa086,0x3f6ed89e,0xbeb8442a,0x3f68bf3c,0xbed53641,
0x3f800000,0x0,0x3f7f4e6d,0xbd96a905,0x3f7d3aac,0xbe164083,0x3f79c79d,0xbe605c13,0x3f74fa0b,0xbe94a031,0x3f6ed89e,0xbeb8442a,0x3f676bd8,0xbedae880,0x3f5ebe05,0xbefc5d27,
0x3f800000,0x0,0x3f7f0e58,0xbdafb680,0x3f7c3b28,0xbe2f10a2,0x3f778bc5,0xbe827dc0,0x3f710908,0xbeac7cd4,0x3f68bf3c,0xbed53641,0x3f5ebe05,0xbefc5d27,0x3f531849,0xbf10d3cd,
0x3f800000,0x0,0x3f7ec46d,0xbdc8bd36,0x3f7b14be,0xbe47c5c2,0x3f74fa0b,0xbe94a031,0x3f6c835e,0xbec3ef15,0x3f61c598,0xbef15aea,0x3f54db31,0xbf0e39da,0x3f45e403,0xbf226799,
0x3f800000,0x0,0x3f7e70b0,0xbde1bc2e,0x3f79c79d,0xbe605c13,0x3f721352,0xbea68f12,0x3f676bd8,0xbedae880,0x3f59f26a,0xbf064b82,0x3f49d112,0xbf1d7fd1,0x3f373a23,0xbf32c8c9,
0x3f800000,0x0,0x3f7e1324,0xbdfab273,0x3f7853f8,0xbe78cfcc,0x3f6ed89e,0xbeb8442a,0x3f61c598,0xbef15aea,0x3f514d3d,0xbf13682a,0x3f3daef9,0xbf2beb4a,0x3f273656,0xbf41d870,
0x3f800000,0x0,0x3f7dabcc,0xbe09cf86,0x3f76ba07,0xbe888e93,0x3f6b4b0c,0xbec9b953,0x3f5b941a,0xbf039c3d,0x3f47de65,0xbf1ff6cb,0x3f3085bb,0xbf396842,0x3f15f6d9,0xbf4f7a1f,
0x3f800000,0x0,0x3f7d3aac,0xbe164083,0x3f74fa0b,0xbe94a031,0x3f676bd8,0xbedae880,0x3f54db31,0xbf0e39da,0x3f3daef9,0xbf2beb4a,0x3f226799,0xbf45e403,0x3f039c3d,0xbf5b941a,
0x3f800000,0x0,0x3f7cbfc9,0xbe22abb6,0x3f731447,0xbea09ae5,0x3f633c5a,0xbeebcbbb,0x3f4d9f02,0xbf187fc0,0x3f32c8c9,0xbf373a23,0x3f13682a,0xbf514d3d,0x3ee0924f,0xbf660f88,
0x3f800000,0x0,0x3f7c3b28,0xbe2f10a2,0x3f710908,0xbeac7cd4,0x3f5ebe05,0xbefc5d27,0x3f45e403,0xbf226799,0x3f273656,0xbf41d870,0x3f039c3d,0xbf5b941a,0x3eb8442a,0xbf6ed89e,
0x3f800000,0x0,0x3f7baccd,0xbe3b6ecf,0x3f6ed89e,0xbeb8442a,0x3f59f26a,0xbf064b82,0x3f3daef9,0xbf2beb4a,0x3f1b02c6,0xbf4bbbf8,0x3ee63375,0xbf64aa59,0x3e8e9a22,0xbf75dec6,
0x3f800000,0x0,0x3f7b14be,0xbe47c5c2,0x3f6c835e,0xbec3ef15,0x3f54db31,0xbf0e39da,0x3f3504f3,0xbf3504f3,0x3f0e39da,0xbf54db31,0x3ec3ef15,0xbf6c835e,0x3e47c5c2,0xbf7b14be,
0x3f800000,0x0,0x3f7a7302,0xbe541501,0x3f6a09a7,0xbecf7bca,0x3f4f7a1f,0xbf15f6d9,0x3f2beb4a,0xbf3daef9,0x3f00e7e4,0xbf5d2d53,0x3ea09ae5,0xbf731447,0x3de1bc2e,0xbf7e70b0,
0x3f800000,0x0,0x3f79c79d,0xbe605c13,0x3f676bd8,0xbedae880,0x3f49d112,0xbf1d7fd1,0x3f226799,0xbf45e403,0x3ee63375,0xbf64aa59,0x3e78cfcc,0xbf7853f8,0x3cc90ab0,0xbf7fec43,
0x3f800000,0x0,0x3f791298,0xbe6c9a7f,0x3f64aa59,0xbee63375,0x3f43e200,0xbf24d225,0x3f187fc0,0xbf4d9f02,0x3ec9b953,0xbf6b4b0c,0x3e2f10a2,0xbf7c3b28,0xbd7b2b74,0xbf7f84ab,
0x3f800000,0x0,0x3f7853f8,0xbe78cfcc,0x3f61c598,0xbef15aea,0x3f3daef9,0xbf2beb4a,0x3f0e39da,0xbf54db31,0x3eac7cd4,0xbf710908,0x3dc8bd36,0xbf7ec46d,0xbe164083,0xbf7d3aac,
0x3f800000,0x0,0x3f778bc5,0xbe827dc0,0x3f5ebe05,0xbefc5d27,0x3f373a23,0xbf32c8c9,0x3f039c3d,0xbf5b941a,0x3e8e9a22,0xbf75dec6,0x3cc90ab0,0xbf7fec43,0xbe6c9a7f,0xbf791298,
0x3f800000,0x0,0x3f76ba07,0xbe888e93,0x3f5b941a,0xbf039c3d,0x3f3085bb,0xbf396842,0x3ef15aea,0xbf61c598,0x3e605c13,0xbf79c79d,0xbd48fb30,0xbf7fb10f,0xbea09ae5,0xbf731447,
0x3f800000,0x0,0x3f75dec6,0xbe8e9a22,0x3f584853,0xbf08f59b,0x3f299415,0xbf3fc767,0x3edae880,0xbf676bd8,0x3e22abb6,0xbf7cbfc9,0xbdfab273,0xbf7e1324,0xbec9b953,0xbf6b4b0c,
0x3f800000,0x0,0x3f74fa0b,0xbe94a031,0x3f54db31,0xbf0e39da,0x3f226799,0xbf45e403,0x3ec3ef15,0xbf6c835e,0x3dc8bd36,0xbf7ec46d,0xbe47c5c2,0xbf7b14be,0xbef15aea,0xbf61c598,
0x3f800000,0x0,0x3f740bdd,0xbe9aa086,0x3f514d3d,0xbf13682a,0x3f1b02c6,0xbf4bbbf8,0x3eac7cd4,0xbf710908,0x3d16c32c,0xbf7fd397,0xbe888e93,0xbf76ba07,0xbf0b9a6b,0xbf5695e5,
0x3f800000,0x0,0x3f731447,0xbea09ae5,0x3f4d9f02,0xbf187fc0,0x3f13682a,0xbf514d3d,0x3e94a031,0xbf74fa0b,0xbcc90ab0,0xbf7fec43,0xbeac7cd4,0xbf710908,0xbf1d7fd1,0xbf49d112,
0x3f800000,0x0,0x3f721352,0xbea68f12,0x3f49d112,0xbf1d7fd1,0x3f0b9a6b,0xbf5695e5,0x3e78cfcc,0xbf7853f8,0xbdafb680,0xbf7f0e58,0xbecf7bca,0xbf6a09a7,0xbf2e3bde,0xbf3b8f3b,
0x3f800000,0x0,0x3f710908,0xbeac7cd4,0x3f45e403,0xbf226799,0x3f039c3d,0xbf5b941a,0x3e47c5c2,0xbf7b14be,0xbe164083,0xbf7d3aac,0xbef15aea,0xbf61c598,0xbf3daef9,0xbf2beb4a,
0x3f800000,0x0,0x3f6ff573,0xbeb263ef,0x3f41d870,0xbf273656,0x3ef6e0cb,0xbf604621,0x3e164083,0xbf7d3aac,0xbe541501,0xbf7a7302,0xbf08f59b,0xbf584853,0xbf4bbbf8,0xbf1b02c6,
0x3f800000,0x0,0x3f6ed89e,0xbeb8442a,0x3f3daef9,0xbf2beb4a,0x3ee63375,0xbf64aa59,0x3dc8bd36,0xbf7ec46d,0xbe888e93,0xbf76ba07,0xbf187fc0,0xbf4d9f02,0xbf584853,0xbf08f59b,
0x3f800000,0x0,0x3f6db293,0xbebe1d4a,0x3f396842,0xbf3085bb,0x3ed53641,0xbf68bf3c,0x3d48fb30,0xbf7fb10f,0xbea68f12,0xbf721352,0xbf273656,0xbf41d870,0xbf633c5a,0xbeebcbbb,
0x3f800000,0x3f800000,0x3f800000,0x3f800000,0x3f800000,0x3f800000,0x3f800000,0x3f800000,0x3f800000,0xbf800000,0x3f800000,0xbf800000,0x3f800000,0xbf800000,0x3f800000,0xbf800000,
0x3f800000,0x3f3504f3,0x0,0xbf3504f3,0xbf800000,0xbf3504f3,0x0,0x3f3504f3,0x0,0xbf3504f3,0xbf800000,0xbf3504f3,0x0,0x3f3504f3,0x3f800000,0x3f3504f3,
0x3f800000,0x0,0xbf800000,0x0,0x3f800000,0x0,0xbf800000,0x0,0x0,0xbf800000,0x0,0x3f800000,0x0,0xbf800000,0x0,0x3f800000,
0x3f800000,0xbf3504f3,0x0,0x3f3504f3,0xbf800000,0x3f3504f3,0x0,0xbf3504f3,0x0,0xbf3504f3,0x3f800000,0xbf3504f3,0x0,0x3f3504f3,0xbf800000,0x3f3504f3,
0x3f800000,0x3f6c835e,0x3f3504f3,0x3ec3ef15,0x0,0xbec3ef15,0xbf3504f3,0xbf6c835e,0x0,0xbec3ef15,0xbf3504f3,0xbf6c835e,0xbf800000,0xbf6c835e,0xbf3504f3,0xbec3ef15,
0x3f800000,0x3ec3ef15,0xbf3504f3,0xbf6c835e,0x0,0x3f6c835e,0x3f3504f3,0xbec3ef15,0x0,0xbf6c835e,0xbf3504f3,0x3ec3ef15,0x3f800000,0x3ec3ef15,0xbf3504f3,0xbf6c835e,
0x3f800000,0xbec3ef15,0xbf3504f3,0x3f6c835e,0x0,0xbf6c835e,0x3f3504f3,0x3ec3ef15,0x0,0xbf6c835e,0x3f3504f3,0x3ec3ef15,0xbf800000,0x3ec3ef15,0x3f3504f3,0xbf6c835e,
0x3f800000,0xbf6c835e,0x3f3504f3,0xbec3ef15,0x0,0x3ec3ef15,0xbf3504f3,0x3f6c835e,0x0,0xbec3ef15,0x3f3504f3,0xbf6c835e,0x3f800000,0xbf6c835e,0x3f3504f3,0xbec3ef15,
};

struct Params {
    const __nv_bfloat16 *wr, *wi, *xb, *lre, *lim, *ldt, *dsk;
    float* out;
};

struct cf { float x, y; };
#define YIELD() asm volatile("pmevent 1;")
#define YS 15
#define YIELD_S1() do { if (YS & 1) YIELD(); } while (0)
#define YIELD_S2() do { if (YS & 2) YIELD(); } while (0)
#define YIELD_S3() do { if (YS & 4) YIELD(); } while (0)
__device__ __forceinline__ uint32_t smem_u32(const void* p) { return (uint32_t)__cvta_generic_to_shared(p); }
__device__ __forceinline__ void mbar_init(uint32_t a, uint32_t c) { asm volatile("mbarrier.init.shared::cta.b64 [%0], %1;" ::"r"(a), "r"(c) : "memory"); }
__device__ __forceinline__ void mbar_expect_tx(uint32_t a, uint32_t b) { asm volatile("mbarrier.arrive.expect_tx.shared::cta.b64 _, [%0], %1;" ::"r"(a), "r"(b) : "memory"); }
__device__ __forceinline__ void mbar_arrive(uint32_t a) { asm volatile("mbarrier.arrive.shared::cta.b64 _, [%0];" ::"r"(a) : "memory"); }
__device__ __forceinline__ uint32_t mbar_try(uint32_t a, uint32_t ph) {
    uint32_t ok;
    asm volatile("{.reg .pred p; mbarrier.try_wait.parity.shared::cta.b64 p, [%1], %2; selp.u32 %0, 1, 0, p;}" : "=r"(ok) : "r"(a), "r"(ph) : "memory");
    return ok;
}
__device__ __forceinline__ void mbar_wait(uint32_t a, uint32_t ph) {
    uint32_t ok, n = 0;
    do { ok = mbar_try(a, ph); } while (!ok && ++n < SPIN_LIMIT);
}
__device__ __forceinline__ void mbar_wait_fast(uint32_t a, uint32_t ph) { if (!mbar_try(a, ph)) mbar_wait(a, ph); }
__device__ __forceinline__ unsigned ld_rlx(const unsigned* p) { unsigned v; asm volatile("ld.relaxed.gpu.global.u32 %0, [%1];" : "=r"(v) : "l"(p) : "memory"); return v; }
__device__ __forceinline__ void wait_cnt(const unsigned* p, unsigned target) {
    unsigned n = 0;
    while ((int)(ld_rlx(p) - target) < 0 && ++n < SPIN_LIMIT) __nanosleep(20);
}
__device__ __forceinline__ void red_hint(unsigned* p) { asm volatile("red.relaxed.gpu.global.add.u32 [%0], 1;" ::"l"(p) : "memory"); }
__device__ __forceinline__ void fence_async() { asm volatile("fence.proxy.async.global;" ::: "memory"); }
__device__ __forceinline__ void fence_async_sm() { asm volatile("fence.proxy.async.shared::cta;" ::: "memory"); }
#define bar_sync(id, n) asm volatile("bar.sync %0, %1;" ::"n"(id), "n"(n) : "memory")
#define bar_arrive(id, n) asm volatile("bar.arrive %0, %1;" ::"n"(id), "n"(n) : "memory")
__device__ __forceinline__ bool elect_one() {
    uint32_t r;
    asm volatile("{.reg .pred p; elect.sync _|p, 0xffffffff; selp.u32 %0, 1, 0, p;}" : "=r"(r));
    return r != 0;
}

__device__ __forceinline__ void tma2d(uint32_t dst, const CUtensorMap* m, int c0, int c1, uint32_t bar) {
    asm volatile("cp.async.bulk.tensor.2d.shared::cluster.global.mbarrier::complete_tx::bytes [%0], [%1, {%3,%4}], [%2];" ::"r"(dst), "l"(m), "r"(bar), "r"(c0), "r"(c1) : "memory");
}
__device__ __forceinline__ void tma2d_mc(uint32_t dst, const CUtensorMap* m, int c0, int c1, uint32_t bar) {
    asm volatile("cp.async.bulk.tensor.2d.shared::cluster.global.mbarrier::complete_tx::bytes.multicast::cluster [%0], [%1, {%3,%4}], [%2], %5;" ::"r"(dst), "l"(m), "r"(bar), "r"(c0), "r"(c1), "h"((uint16_t)3) : "memory");
}
__device__ __forceinline__ void tma4d_mc(uint32_t dst, const CUtensorMap* m, int c0, int c1, int c2, int c3, uint32_t bar) {
    asm volatile("cp.async.bulk.tensor.4d.shared::cluster.global.mbarrier::complete_tx::bytes.multicast::cluster [%0], [%1, {%3,%4,%5,%6}], [%2], %7;" ::"r"(dst), "l"(m), "r"(bar), "r"(c0), "r"(c1), "r"(c2), "r"(c3), "h"((uint16_t)3) : "memory");
}
__device__ __forceinline__ void tma4d(uint32_t dst, const CUtensorMap* m, int c0, int c1, int c2, int c3, uint32_t bar) {
    asm volatile("cp.async.bulk.tensor.4d.shared::cluster.global.mbarrier::complete_tx::bytes [%0], [%1, {%3,%4,%5,%6}], [%2];" ::"r"(dst), "l"(m), "r"(bar), "r"(c0), "r"(c1), "r"(c2), "r"(c3) : "memory");
}
__device__ __forceinline__ void tma2d_st(const CUtensorMap* m, int c0, int c1, uint32_t src) {
    asm volatile("cp.async.bulk.tensor.2d.global.shared::cta.bulk_group [%0, {%2,%3}], [%1];" ::"l"(m), "r"(src), "r"(c0), "r"(c1) : "memory");
}
__device__ __forceinline__ void tma3d_st(const CUtensorMap* m, int c0, int c1, int c2, uint32_t src) {
    asm volatile("cp.async.bulk.tensor.3d.global.shared::cta.bulk_group [%0, {%2,%3,%4}], [%1];" ::"l"(m), "r"(src), "r"(c0), "r"(c1), "r"(c2) : "memory");
}
__device__ __forceinline__ void tma5d(uint32_t dst, const CUtensorMap* m, int c0, int c1, int c2, int c3, int c4, uint32_t bar) {
    asm volatile("cp.async.bulk.tensor.5d.shared::cluster.global.mbarrier::complete_tx::bytes [%0], [%1, {%3,%4,%5,%6,%7}], [%2];" ::"r"(dst), "l"(m), "r"(bar), "r"(c0), "r"(c1), "r"(c2), "r"(c3), "r"(c4) : "memory");
}
__device__ __forceinline__ void tma5d_mc(uint32_t dst, const CUtensorMap* m, int c0, int c1, int c2, int c3, int c4, uint32_t bar) {
    asm volatile("cp.async.bulk.tensor.5d.shared::cluster.global.mbarrier::complete_tx::bytes.multicast::cluster [%0], [%1, {%3,%4,%5,%6,%7}], [%2], %8;" ::"r"(dst), "l"(m), "r"(bar), "r"(c0), "r"(c1), "r"(c2), "r"(c3), "r"(c4), "h"((uint16_t)3) : "memory");
}
__device__ __forceinline__ void bulk_ld(uint32_t dst, const void* src, uint32_t n, uint32_t bar) {
    asm volatile("cp.async.bulk.shared::cluster.global.mbarrier::complete_tx::bytes [%0], [%1], %2, [%3];" ::"r"(dst), "l"(src), "r"(n), "r"(bar) : "memory");
}
__device__ __forceinline__ void bulk_st(void* dst, uint32_t src, uint32_t n) {
    asm volatile("cp.async.bulk.global.shared::cta.bulk_group [%0], [%1], %2;" ::"l"(dst), "r"(src), "r"(n) : "memory");
}
__device__ __forceinline__ void bulk_commit() { asm volatile("cp.async.bulk.commit_group;" ::: "memory"); }
__device__ __forceinline__ void bulk_wait_read() { asm volatile("cp.async.bulk.wait_group.read 0;" ::: "memory"); }
__device__ __forceinline__ void bulk_wait_all() { asm volatile("cp.async.bulk.wait_group 0;" ::: "memory"); }
__device__ __forceinline__ void stsm4(uint32_t a, uint32_t r0, uint32_t r1, uint32_t r2, uint32_t r3) {
    asm volatile("stmatrix.sync.aligned.m8n8.x4.shared.b16 [%0], {%1,%2,%3,%4};" ::"r"(a), "r"(r0), "r"(r1), "r"(r2), "r"(r3) : "memory");
}
__device__ __forceinline__ void sts128(uint32_t a, uint32_t r0, uint32_t r1, uint32_t r2, uint32_t r3) {
    asm volatile("st.shared.v4.b32 [%0], {%1,%2,%3,%4};" ::"r"(a), "r"(r0), "r"(r1), "r"(r2), "r"(r3) : "memory");
}
__device__ __forceinline__ void lds128f(uint32_t a, float& x, float& y, float& z, float& u) { asm volatile("ld.shared.v4.f32 {%0,%1,%2,%3}, [%4];" : "=f"(x), "=f"(y), "=f"(z), "=f"(u) : "r"(a) : "memory"); }
__device__ __forceinline__ cf lds_cf(uint32_t a) { cf v; asm volatile("ld.shared.v2.f32 {%0,%1}, [%2];" : "=f"(v.x), "=f"(v.y) : "r"(a) : "memory"); return v; }
__device__ __forceinline__ void stg128(void* a, uint32_t r0, uint32_t r1, uint32_t r2, uint32_t r3) {
    asm volatile("st.global.v4.b32 [%0], {%1,%2,%3,%4};" ::"l"(a), "r"(r0), "r"(r1), "r"(r2), "r"(r3) : "memory");
}
__device__ __forceinline__ uint4 ldtab(int word) { return __ldg((const uint4*)(g_tab + word)); }
__device__ __forceinline__ void load_tw(cf (&tw)[8], int k1) {
#pragma unroll
    for (int i = 0; i < 4; i++) {
        const uint4 v = ldtab(TAB_TW + k1 * 16 + i * 4);
        tw[2 * i] = {__uint_as_float(v.x), __uint_as_float(v.y)};
        tw[2 * i + 1] = {__uint_as_float(v.z), __uint_as_float(v.w)};
    }
}
__device__ __forceinline__ void load_T(cf (&T)[8], int t7) {
#pragma unroll
    for (int i = 0; i < 4; i++)
        asm volatile("ld.global.nc.v4.f32 {%0,%1,%2,%3}, [%4];" : "=f"(T[2 * i].x), "=f"(T[2 * i].y), "=f"(T[2 * i + 1].x), "=f"(T[2 * i + 1].y) : "l"(g_tab + TAB_T + i * 512 + t7 * 4));
}
__device__ __forceinline__ float lds_bf(uint32_t a) { unsigned short v; asm volatile("ld.shared.u16 %0, [%1];" : "=h"(v) : "r"(a)); return __uint_as_float((uint32_t)v << 16); }
__device__ __forceinline__ unsigned get_epoch(uint32_t bars) {
    mbar_wait(bars + B_EP, 0);
    unsigned e;
    asm volatile("ld.shared.u32 %0, [%1];" : "=r"(e) : "r"(bars + B_EPOCH) : "memory");
    return e;
}
__device__ __forceinline__ void sts64f(uint32_t a, float x, float y) { asm volatile("st.shared.v2.f32 [%0], {%1,%2};" ::"r"(a), "f"(x), "f"(y) : "memory"); }
__device__ __forceinline__ uint32_t pk(float lo, float hi) { uint32_t r; asm("cvt.rn.bf16x2.f32 %0, %1, %2;" : "=r"(r) : "f"(hi), "f"(lo)); return r; }
__device__ __forceinline__ float bf2f(unsigned short v) { return __uint_as_float((uint32_t)v << 16); }

__device__ __forceinline__ uint64_t mkdesc(uint32_t addr, uint32_t lbo, uint32_t sbo, uint32_t swz) {
    return (uint64_t)((addr & 0x3FFFF) >> 4) | ((uint64_t)(lbo >> 4) << 16) | ((uint64_t)(sbo >> 4) << 32) | ((uint64_t)swz << 62);
}
__device__ __forceinline__ uint64_t opaque(uint64_t v) { asm volatile("" : "+l"(v)); return v; }
__device__ __forceinline__ uint32_t opaque32(uint32_t v) { asm volatile("" : "+r"(v)); return v; }
__device__ __forceinline__ void wg_fence() { asm volatile("wgmma.fence.sync.aligned;" ::: "memory"); }
__device__ __forceinline__ void wg_commit() { asm volatile("wgmma.commit_group.sync.aligned;" ::: "memory"); }
template <int N> __device__ __forceinline__ void wg_wait() { asm volatile("wgmma.wait_group.sync.aligned %0;" ::"n"(N) : "memory"); }
template <int N> __device__ __forceinline__ void pin(float (&d)[N]) {
#pragma unroll
    for (int i = 0; i < N; i++) asm volatile("" : "+f"(d[i])::"memory");
}
template <int N> __device__ __forceinline__ void pinu(uint32_t (&d)[N]) {
#pragma unroll
    for (int i = 0; i < N; i++) asm volatile("" : "+r"(d[i])::"memory");
}

#define R8(d, o) "+f"(d[o]), "+f"(d[o + 1]), "+f"(d[o + 2]), "+f"(d[o + 3]), "+f"(d[o + 4]), "+f"(d[o + 5]), "+f"(d[o + 6]), "+f"(d[o + 7])
#define L8 "%0,%1,%2,%3,%4,%5,%6,%7"
#define L32 L8 ",%8,%9,%10,%11,%12,%13,%14,%15,%16,%17,%18,%19,%20,%21,%22,%23,%24,%25,%26,%27,%28,%29,%30,%31"
#define L56 L32 ",%32,%33,%34,%35,%36,%37,%38,%39,%40,%41,%42,%43,%44,%45,%46,%47,%48,%49,%50,%51,%52,%53,%54,%55"
#define L64 L56 ",%56,%57,%58,%59,%60,%61,%62,%63"

template <int O, int TA, int TB, int N> __device__ __forceinline__ void mma128_ss(float (&d)[N], uint64_t da, uint64_t db, int sc) {
    asm volatile("{.reg .pred p; setp.ne.b32 p, %66, 0;\n"
                 "wgmma.mma_async.sync.aligned.m64n128k16.f32.bf16.bf16 {" L64 "}, %64, %65, p, 1, 1, %67, %68;}"
                 : R8(d, O), R8(d, O + 8), R8(d, O + 16), R8(d, O + 24), R8(d, O + 32), R8(d, O + 40), R8(d, O + 48), R8(d, O + 56)
                 : "l"(da), "l"(db), "r"(sc), "n"(TA), "n"(TB));
}
template <int TB> __device__ __forceinline__ void mma128_rs(float (&d)[64], uint32_t a0, uint32_t a1, uint32_t a2, uint32_t a3, uint64_t db, int sc) {
    asm volatile("{.reg .pred p; setp.ne.b32 p, %69, 0;\n"
                 "wgmma.mma_async.sync.aligned.m64n128k16.f32.bf16.bf16 {" L64 "}, {%64,%65,%66,%67}, %68, p, 1, 1, %70;}"
                 : R8(d, 0), R8(d, 8), R8(d, 16), R8(d, 24), R8(d, 32), R8(d, 40), R8(d, 48), R8(d, 56)
                 : "r"(a0), "r"(a1), "r"(a2), "r"(a3), "l"(db), "r"(sc), "n"(TB));
}
template <int TB> __device__ __forceinline__ void mma64_rs(float (&d)[32], uint32_t a0, uint32_t a1, uint32_t a2, uint32_t a3, uint64_t db, int sc) {
    asm volatile("{.reg .pred p; setp.ne.b32 p, %37, 0;\n"
                 "wgmma.mma_async.sync.aligned.m64n64k16.f32.bf16.bf16 {" L32 "}, {%32,%33,%34,%35}, %36, p, 1, 1, %38;}"
                 : R8(d, 0), R8(d, 8), R8(d, 16), R8(d, 24)
                 : "r"(a0), "r"(a1), "r"(a2), "r"(a3), "l"(db), "r"(sc), "n"(TB));
}
__device__ __forceinline__ void mma112_ss(float (&d)[64], uint64_t da, uint64_t db, int sc) {
    asm volatile("{.reg .pred p; setp.ne.b32 p, %58, 0;\n"
                 "wgmma.mma_async.sync.aligned.m64n112k16.f32.bf16.bf16 {" L56 "}, %56, %57, p, 1, 1, 0, 1;}"
                 : R8(d, 8), R8(d, 16), R8(d, 24), R8(d, 32), R8(d, 40), R8(d, 48), R8(d, 56)
                 : "l"(da), "l"(db), "r"(sc));
}
__device__ __forceinline__ void mma16_rs(float (&d)[64], uint32_t a0, uint32_t a1, uint32_t a2, uint32_t a3, uint64_t db, int sc) {
    asm volatile("{.reg .pred p; setp.ne.b32 p, %13, 0;\n"
                 "wgmma.mma_async.sync.aligned.m64n16k16.f32.bf16.bf16 {" L8 "}, {%8,%9,%10,%11}, %12, p, 1, 1, 1;}"
                 : R8(d, 0)
                 : "r"(a0), "r"(a1), "r"(a2), "r"(a3), "l"(db), "r"(sc));
}

__device__ __forceinline__ cf cmul(cf a, cf b) { return {fmaf(a.x, b.x, -a.y * b.y), fmaf(a.x, b.y, a.y * b.x)}; }
__device__ __forceinline__ cf cmulc(cf a, cf b) { return {fmaf(a.x, b.x, a.y * b.y), fmaf(a.y, b.x, -a.x * b.y)}; }
__device__ __forceinline__ cf cfma(cf a, cf b, cf c) { return {fmaf(a.x, b.x, fmaf(-a.y, b.y, c.x)), fmaf(a.x, b.y, fmaf(a.y, b.x, c.y))}; }
__device__ __forceinline__ cf csq(cf a) { return {fmaf(a.x, a.x, -a.y * a.y), (a.x + a.x) * a.y}; }
__device__ __forceinline__ cf cadd(cf a, cf b) { return {a.x + b.x, a.y + b.y}; }
__device__ __forceinline__ cf csub(cf a, cf b) { return {a.x - b.x, a.y - b.y}; }
__device__ __forceinline__ cf twice_minus(cf a, cf s) { return {fmaf(2.f, a.x, -s.x), fmaf(2.f, a.y, -s.y)}; }
__device__ __forceinline__ cf twid(int m, int M) {
    int r = ((m + M / 2) & (M - 1)) - M / 2;
    float s, c;
    __sincosf((float)r * (-6.283185307179586f / (float)M), &s, &c);
    return {c, s};
}
template <bool TW> __device__ __forceinline__ void dft8(cf (&v)[8], const cf (&tw)[8]) {
    const float s = 0.70710678118654752f;
    cf a0, a1, a2, a3, a4, a5, a6, a7;
    if (TW) {
        const cf t1 = cmul(v[1], tw[1]), t2 = cmul(v[2], tw[2]), t3 = cmul(v[3], tw[3]);
        a0 = cfma(v[4], tw[4], v[0]); a1 = twice_minus(v[0], a0);
        a2 = cfma(v[6], tw[6], t2); a3 = twice_minus(t2, a2);
        a4 = cfma(v[5], tw[5], t1); a5 = twice_minus(t1, a4);
        a6 = cfma(v[7], tw[7], t3); a7 = twice_minus(t3, a6);
    } else {
        a0 = cadd(v[0], v[4]); a1 = csub(v[0], v[4]); a2 = cadd(v[2], v[6]); a3 = csub(v[2], v[6]);
        a4 = cadd(v[1], v[5]); a5 = csub(v[1], v[5]); a6 = cadd(v[3], v[7]); a7 = csub(v[3], v[7]);
    }
    cf e0 = cadd(a0, a2), e2 = csub(a0, a2), e1 = {a1.x + a3.y, a1.y - a3.x}, e3 = {a1.x - a3.y, a1.y + a3.x};
    cf o0 = cadd(a4, a6), o2 = csub(a4, a6), o1 = {a5.x + a7.y, a5.y - a7.x}, o3 = {a5.x - a7.y, a5.y + a7.x};
    cf t1 = {o1.x + o1.y, o1.y - o1.x}, t3 = {o3.y - o3.x, -o3.x - o3.y};
    v[0] = cadd(e0, o0); v[4] = csub(e0, o0);
    v[1] = {fmaf(s, t1.x, e1.x), fmaf(s, t1.y, e1.y)}; v[5] = {fmaf(-s, t1.x, e1.x), fmaf(-s, t1.y, e1.y)};
    v[2] = {e2.x + o2.y, e2.y - o2.x}; v[6] = {e2.x - o2.y, e2.y + o2.x};
    v[3] = {fmaf(s, t3.x, e3.x), fmaf(s, t3.y, e3.y)}; v[7] = {fmaf(-s, t3.x, e3.x), fmaf(-s, t3.y, e3.y)};
}

template <int H> __device__ __forceinline__ void prescale(float (&d)[128], cf gam) {
#pragma unroll
    for (int r = 2 * H; r < 64; r += 4) {
        asm volatile("{.reg .f32 s, t, u, v; mul.f32 s, %5, %1; mul.f32 u, %5, %3; mul.f32 t, %4, %1; mul.f32 v, %4, %3; neg.f32 t, t; neg.f32 v, v;\n"
                     "fma.rn.f32 %1, %5, %0, t; fma.rn.f32 %3, %5, %2, v; fma.rn.f32 %0, %4, %0, s; fma.rn.f32 %2, %4, %2, u;}"
                     : "+f"(d[r]), "+f"(d[64 + r]), "+f"(d[r + 1]), "+f"(d[65 + r]) : "f"(gam.x), "f"(gam.y));
        YIELD_S2();
    }
}
template <int H> __device__ __forceinline__ void scan2(float (&d)[128], cf lam, cf st, uint8_t* hptr, uint32_t hm, uint32_t hb, uint32_t& keep) {
    uint32_t hp[32];
#pragma unroll
    for (int u = 0; u < 32; u++) {
        const int r = 4 * (u >> 1) + 2 * H + (u & 1);
        st = cfma(lam, st, {d[r], d[64 + r]});
        d[r] = st.x; d[64 + r] = st.y;
        if ((u & 7) == 7) {
            const int jj = u >> 3;
#pragma unroll
            for (int ri = 0; ri < 2; ri++) {
                const int a = 64 * ri + 16 * jj + 2 * H, o = 8 * jj + 4 * ri;
                hp[o] = pk(d[a], d[a + 4]); hp[o + 1] = pk(d[a + 8], d[a + 12]); hp[o + 2] = pk(d[a + 1], d[a + 5]); hp[o + 3] = pk(d[a + 9], d[a + 13]);
                hp[o + jj] = (hp[o + jj] & hm) | hb;
                stg128(hptr + ri * 16384 + (jj >> 1) * 8192 + (jj & 1) * 512, hp[o], hp[o + 1], hp[o + 2], hp[o + 3]);
            }
            YIELD_S3();
            if (jj > 0) {
#pragma unroll
                for (int i = 8 * jj - 8; i < 8 * jj; i += 2) asm volatile("lop3.b32 %0, %0, %1, %2, 0x80;" : "+r"(keep) : "r"(hp[i]), "r"(hp[i + 1]));
            }
        }
    }
}

__device__ __forceinline__ void bid2tile(int b, int& tc, int& cb) {
    int g, t;
    const int c = b >> 1;
    if (c < 4) { g = 0; t = 4 + c; }
    else if (c < 36) { g = (c + 3) & 7; t = (c - 4) >> 3; }
    else { g = 1 + (c - 30) % 7; t = 4 + (c - 36) / 7; }
    cb = t;
    tc = 2 * g + (b & 1);
}
__device__ __forceinline__ int pos_of(int n) { return (n & 24) + 4 * (n & 1) + ((n >> 1) & 3); }
__device__ __forceinline__ int kappa_of(int sig) {
    int k1 = sig & 31, r = sig >> 5;
    return k1 ? k1 + 64 * r : (r < 4 ? 64 * r : 32 + 64 * (r - 4));
}
__device__ __forceinline__ int slot3_of(int kap, int& cj) {
    int m = kap & 15;
    cj = (m > 8) || ((m & 7) == 0 && kap > 256);
    int kk = cj ? 512 - kap : kap;
    m = kk & 15;
    if (kk == 256) return 0;
    return m == 0 ? pos_of(kk >> 4) : (m == 8 ? pos_of(16 + (kk >> 4)) : m * 32 + pos_of(kk >> 4));
}

template <int NS> __device__ __forceinline__ uint32_t tags_bad(uint32_t buf, uint32_t tag, int t7) {
    uint32_t bad = 0;
#pragma unroll
    for (int i = 0; i < NS; i++) {
        uint32_t v;
        asm volatile("ld.shared.u32 %0, [%1];" : "=r"(v) : "r"(buf + t7 * 32 + (((t7 >> 2) & 1) << 4) + i * 4096) : "memory");
        bad |= v ^ tag;
    }
    return bad & 1;
}
__device__ __forceinline__ bool wg_all_ok(uint32_t bad, int id) {
    uint32_t ok;
    asm volatile("{.reg .pred p, q; setp.eq.u32 q, %1, 0; barrier.red.and.aligned.pred p, %2, 128, q; selp.u32 %0, 1, 0, p;}" : "=r"(ok) : "r"(bad), "r"(id) : "memory");
    return ok != 0;
}
__device__ __forceinline__ void load_w_rows(uint32_t dst, const CUtensorMap* mr, const CUtensorMap* mi, int kap, uint32_t bar) {
    mbar_expect_tx(bar, 8 * WPITCH);
    tma2d(dst, mr, (kap * 1026 >> 4) * 2, 0, bar);
    tma2d(dst + 4 * WPITCH, mi, (kap * 1026 >> 4) * 2, 0, bar);
}
__device__ __forceinline__ void prefetch_w_rows(const CUtensorMap* mr, const CUtensorMap* mi, int kap) {
    asm volatile("cp.async.bulk.prefetch.tensor.2d.L2.global [%0, {%1,%2}];" ::"l"(mr), "r"((kap * 1026 >> 4) * 2), "r"(0) : "memory");
    asm volatile("cp.async.bulk.prefetch.tensor.2d.L2.global [%0, {%1,%2}];" ::"l"(mi), "r"((kap * 1026 >> 4) * 2), "r"(0) : "memory");
}
#define SB0 1024
#define RDESC(off) (0x4000004000010000ull + (uint64_t)(SB0 / 16 + (off)))
#define HDESC(off) (0x8000004000200000ull + (uint64_t)(SB0 / 16 + (off)))
template <int O, int TA, int SC, int DA, int DB> __device__ __forceinline__ void mma_g(float (&d)[128]) {
    asm volatile("{.reg .b64 da, db; mov.b64 da, %64; mov.b64 db, %65;\n"
                 "wgmma.mma_async.sync.aligned.m64n128k16.f32.bf16.bf16 {" L64 "}, da, db, %66, 1, 1, %67, 0;}"
                 : R8(d, O), R8(d, O + 8), R8(d, O + 16), R8(d, O + 24), R8(d, O + 32), R8(d, O + 40), R8(d, O + 48), R8(d, O + 56)
                 : "n"(TA ? HDESC(DA) : RDESC(DA)), "n"(RDESC(DB)), "n"(SC), "n"(TA));
}
struct Ring {
    uint32_t full, rel;
    bool sig;
};
__device__ __forceinline__ void ring_release(const Ring& r, int slot) {
    if (r.sig) asm volatile("mbarrier.arrive.shared::cluster.b64 _, [%0];" ::"r"(r.rel + 8 * slot) : "memory");
}
__device__ __forceinline__ void peek(uint32_t a, uint32_t ph) { asm volatile("mbarrier.test_wait.parity.shared::cta.b64 pk, [%0], %1;" ::"r"(a), "r"(ph) : "memory"); }
__device__ __forceinline__ void peek_wait(uint32_t a, uint32_t ph) {
    asm volatile("{.reg .u32 n; @pk bra DONE; mov.u32 n, 0;\n"
                 "LOOP: mbarrier.try_wait.parity.shared::cta.b64 pk, [%0], %1; @pk bra DONE; add.u32 n, n, 1; setp.gt.u32 pk, n, %2; @!pk bra LOOP;\n"
                 "DONE: }" ::"r"(a), "r"(ph), "n"(SPIN_LIMIT) : "memory");
}
#define SL(k) ((k) % NST)
#define PH(k) (((k) / NST) & 1)
#define HANDPOS 5
template <int TA, int SC, int K, int HAND> __device__ __forceinline__ void gemm_step(float (&d)[128], Ring& r, uint32_t f, bool rel, bool hand = false) {
    const int KA = TA ? 128 : 2, a = SL(K) * 2048;
    wg_fence();
    mma_g<0, TA, SC, a, a + 1024>(d);
    mma_g<64, TA, SC, a + 512, a + 1024>(d);
    wg_commit();
    wg_wait<1>();
    if (rel) ring_release(r, SL(K + NST - 1));
    mma_g<0, TA, 1, a + KA, a + 1026>(d);
    peek(r.full + 8 * SL(K + 1), PH(K + 1) ^ f);
    mma_g<64, TA, 1, a + 512 + KA, a + 1026>(d);
    if (HAND && HANDPOS == 4 && hand) bar_arrive(HAND, 256);
    mma_g<0, TA, 1, a + 2 * KA, a + 1028>(d);
    if (HAND && HANDPOS == 5 && hand) bar_arrive(HAND, 256);
    mma_g<64, TA, 1, a + 512 + 2 * KA, a + 1028>(d);
    if (HAND && HANDPOS == 6 && hand) bar_arrive(HAND, 256);
    mma_g<0, TA, 1, a + 3 * KA, a + 1030>(d);
    if (HAND && HANDPOS == 7 && hand) bar_arrive(HAND, 256);
    mma_g<64, TA, 1, a + 512 + 3 * KA, a + 1030>(d);
    wg_commit();
    if (!HAND || !hand) peek_wait(r.full + 8 * SL(K + 1), PH(K + 1) ^ f);
}
template <int K0, class F> __device__ __forceinline__ void gemm1(float (&d)[128], Ring& r, F hook) {
    mbar_wait_fast(r.full + 8 * SL(K0), PH(K0));
    gemm_step<0, 0, K0, 0>(d, r, 0, false);
#pragma unroll 1
    for (int it = 0; it < 3; it++) {
        const uint32_t f = it & 1;
        gemm_step<0, 1, K0 + 1, 0>(d, r, f, true);
        gemm_step<0, 1, K0 + 2, 0>(d, r, f, true);
        gemm_step<0, 1, K0 + 3, 0>(d, r, f, true);
        if (it == 2) hook();
        gemm_step<0, 1, K0 + 4, 0>(d, r, f, true);
        gemm_step<0, 1, K0 + 5, K0 ? 2 : 1>(d, r, f, true, it == 2);
    }
}
template <int O, int K, int J> __device__ __forceinline__ void mma_h(float (&y)[128]) { mma_g<O, 1, 1, SL(K) * 2048 + O * 8 + 128 * J, SL(K) * 2048 + 1024 + 2 * J>(y); }
template <int O, int K> __device__ __forceinline__ void half_step(float (&y)[128]) { mma_h<O, K, 0>(y); mma_h<O, K, 1>(y); mma_h<O, K, 2>(y); mma_h<O, K, 3>(y); }
template <int R, int U> __device__ __forceinline__ void out_piece(float (&y)[128], const uint32_t (&dd)[16], uint32_t x0, uint32_t x1, float* op) {
    const int i = 64 * (R >> 1) + 8 * U + 2 * (R & 1);
    asm("mul.rn.bf16x2 %0, %0, %1;" : "+r"(x0) : "r"(dd[2 * U]));
    asm("mul.rn.bf16x2 %0, %0, %1;" : "+r"(x1) : "r"(dd[2 * U + 1]));
    asm volatile("st.global.v4.f32 [%0], {%1,%2,%3,%4};" ::"l"(op + (32 * (R & 1) + 16 * (R >> 1)) * 2048 + 16 * U),
                 "f"(y[i] + __uint_as_float(x0 << 16)), "f"(y[i + 1] + __uint_as_float(x0 & 0xffff0000u)),
                 "f"(y[i + 4] + __uint_as_float(x1 << 16)), "f"(y[i + 5] + __uint_as_float(x1 & 0xffff0000u)) : "memory");
}
template <int R, int U0> __device__ __forceinline__ void load_x4(uint32_t (&xx)[8], uint32_t xa) {
#pragma unroll
    for (int u = 0; u < 4; u++)
        asm volatile("ld.shared.v2.b32 {%0,%1}, [%2];" : "=r"(xx[2 * u]), "=r"(xx[2 * u + 1]) : "r"((xa ^ (u << 5)) + (3 - R) * 8192 + U0 * 1024) : "memory");
}
__device__ __forceinline__ Ring ring_at(uint32_t sb, int k) {
    Ring r;
    r.full = sb + OFF_BAR + B_FULL;
    asm("mapa.shared::cluster.u32 %0, %1, %2;" : "=r"(r.rel) : "r"(sb + OFF_BAR + B_EMPTY), "r"((threadIdx.x >> 5) & 1));
    r.sig = (threadIdx.x & 95) == 0;
    return r;
}

__global__ void __cluster_dims__(2, 1, 1) __launch_bounds__(512, 1)
fused_kernel(const __grid_constant__ CUtensorMap tmX, const __grid_constant__ CUtensorMap tmBre, const __grid_constant__ CUtensorMap tmBim,
             const __grid_constant__ CUtensorMap tmCre, const __grid_constant__ CUtensorMap tmCim, const __grid_constant__ CUtensorMap tmXd,
             const __grid_constant__ CUtensorMap tmUst, const __grid_constant__ CUtensorMap tmVst,
             const __grid_constant__ CUtensorMap tmWr, const __grid_constant__ CUtensorMap tmWi,
             const __grid_constant__ CUtensorMap tmXA, const Params p) {
    extern __shared__ __align__(1024) uint8_t smraw[];
    const uint32_t sb = smem_u32(smraw);
    asm volatile(".reg .pred pk;");
    if ((sb & 0xFFFFFF) != SB0) return;
    const uint32_t bars = sb + OFF_BAR;
    const int tid = threadIdx.x, bid = blockIdx.x;
    const int wg = __shfl_sync(~0u, tid >> 7, 0), w = __shfl_sync(~0u, tid >> 5, 0) & 3, lane = tid & 31, g = lane >> 2, q = lane & 3;
    const bool extra = bid >= 128;
    int tc = 0, cb = 0;
    if (!extra) bid2tile(bid, tc, cb);
    const int fb = bid >> 5, fcb = bid & 31, fpos = pos_of(fcb);

    if (wg == 3) {
        asm volatile("setmaxnreg.dec.sync.aligned.u32 24;");
        if (w == 2) {
            if (lane < 4) asm volatile("prefetch.tensormap [%0];" ::"l"(lane == 0 ? &tmX : (lane == 1 ? &tmBre : (lane == 2 ? &tmBim : &tmXA))) : "memory");
        } else if (elect_one()) {
            if (w == 0) {
#pragma unroll
                for (int s = 0; s < NST; s++) { mbar_init(bars + B_FULL + s * 8, 1); mbar_init(bars + B_EMPTY + s * 8, 2); }
                mbar_init(bars + B_XIN, 1); mbar_init(bars + B_XIN + 8, 1);
            } else if (w == 1) {
#pragma unroll
                for (int o = B_XD; o < B_WSP; o += 8) mbar_init(bars + o, (o == B_LAM || o == B_STG) ? 4 : (o == B_STGU ? 8 : 1));
#pragma unroll
                for (int o = B_HL; o < B_HL + 80; o += 8) mbar_init(bars + o, 1);
            } else {
#pragma unroll
                for (int o = B_WSP; o < B_EPOCH; o += 8) if (o < B_XIN || o >= B_VIN) mbar_init(bars + o, (o >= B_WFREE && o < B_WD) ? 4 : 1);
            }
            asm volatile("fence.mbarrier_init.release.cluster;" ::: "memory");
            fence_async_sm();
        }
        __syncwarp();
        asm volatile("barrier.cluster.arrive.relaxed.aligned;" ::: "memory");
        if (w == 0 && !extra) {
            if (elect_one()) {
                mbar_expect_tx(bars + B_XIN, 16384);
                mbar_expect_tx(bars + B_XIN + 8, 16384);
#pragma unroll 1
                for (int k = 0; k < 2; k++) {
                    mbar_expect_tx(bars + B_FULL + k * 8, 32768);
                    tma5d(sb + k * 32768 + 16384, &tmX, k * 64, 0, 0, 0, tc, bars + B_FULL + k * 8);
                    if (k == 0) {
                        tma4d(sb + k * 32768, &tmBre, k * 64, 0, 0, cb * 4, bars + B_FULL + k * 8);
                        tma4d(sb + k * 32768 + 8192, &tmBim, k * 64, 0, 0, cb * 4, bars + B_FULL + k * 8);
                    }
                }
            }
            __syncwarp();
        }
        asm volatile("barrier.cluster.wait.aligned;" ::: "memory");
        if (bid == 129) return;
        if (w == 0) {
            if (!extra && elect_one()) {
                int s = 0, ph = 0;
                const int rank = bid & 1;
                STAMP(56);
#pragma unroll 1
                for (int k = 0; k < NST; k++) {
                    if (k >= 2) mbar_expect_tx(bars + B_FULL + k * 8, 32768);
                    if (k > 0) tma4d_mc(sb + k * 32768 + rank * 8192, rank ? &tmBim : &tmBre, k * 64, 0, 0, cb * 4, bars + B_FULL + k * 8);
                    if (k >= 2) tma5d(sb + k * 32768 + 16384, &tmX, k * 64, 0, 0, 0, tc, bars + B_FULL + k * 8);
                }
#pragma unroll 1
                for (int i = 0; i < 2; i++) tma4d(sb + OFF_F + i * 4096, &tmXA, fcb * 32 + (i >> 2) * 16, 0, (i & 3) * 2, fb, bars + B_XIN + (i >> 2) * 8);
#pragma unroll 1
                for (int k = NST; k < 64; k++) {
                    const uint32_t fbar = bars + B_FULL + s * 8, a = sb + s * 32768;
                    mbar_wait(bars + B_EMPTY + s * 8, ph);
                    if (k < 32) {
                        const int kk = (k & 15) * 64;
                        mbar_expect_tx(fbar, 32768);
                        tma4d_mc(a + rank * 8192, rank ? &tmBim : &tmBre, kk, 0, (k >> 4) * 2, cb * 4, fbar);
                        tma5d(a + 16384, &tmX, kk, 0, 0, 0, tc, fbar);
                    } else {
                        const int kk = k - 32;
                        asm volatile("mbarrier.expect_tx.shared::cta.b64 [%0], 16384;" ::"r"(fbar) : "memory");
                        tma5d_mc(a + 16384 + rank * 8192, (kk & 1) ? &tmCim : &tmCre, (kk >> 1) * 64, 0, 0, 0, cb * 8 + rank * 4, fbar);
                        if ((kk & 7) == 0) { mbar_wait(bars + B_HOWN + kk, 0); STAMPR(45 + (kk >> 3)); }
                        mbar_expect_tx(bars + B_HL + s * 16 + (kk & 1) * 8, 16384);
                        bulk_ld(a, g_H + (size_t)(tc * 32 + kk) * 16384, 16384, bars + B_HL + s * 16 + (kk & 1) * 8);
                    }
                    if (k < NST + 6) {
                        const int i = k - NST + 2;
                        tma4d(sb + OFF_F + i * 4096, &tmXA, fcb * 32 + (i >> 2) * 16, 0, (i & 3) * 2, fb, bars + B_XIN + (i >> 2) * 8);
                    }
                    if (k == LDK) mbar_arrive(bars + B_LDONE);
                    if (++s == NST) { s = 0; ph ^= 1; }
                }
            }
        } else if (w == 1) {
          if (elect_one()) {
            unsigned ep;
            asm volatile("ld.relaxed.gpu.global.u32 %0, [%1];" : "=r"(ep) : "l"(g_epoch + bid * 8) : "memory");
            ep++;
            asm volatile("st.relaxed.gpu.global.u32 [%0], %1;" ::"l"(g_epoch + bid * 8), "r"(ep) : "memory");
            asm volatile("st.shared.u32 [%0], %1;" ::"r"(bars + B_EPOCH), "r"(ep) : "memory");
            mbar_arrive(bars + B_EP);
            if (!extra) mbar_wait(bars + B_STGU, 0);
            const int kap0 = extra ? 0 : kappa_of(bid * 2), kap1 = extra ? 256 : kappa_of(bid * 2 + 1);
            const uint8_t* usrc = g_U + (size_t)(extra ? 0 : bid * 32768);
            if (!extra) {
                STAMP(21);
#pragma unroll 1
                for (int r = 0; r < 256 / UBOX; r++) {
                    tma2d_st(&tmUst, fb * 2048 + fpos * 64, r * UBOX, sb + OFF_P + r * (UBOX * 128));
                    if (r == 256 / UBOX - 1) red_hint(g_cnt);
                    if (r < 256 / UBOX - 1) __nanosleep(PACE_U);
                }
                bulk_commit();
                bulk_wait_read();
                STAMP(40);
                STAMP(41);
            }
            mbar_expect_tx(bars + B_FG, 8192);
            bulk_ld(sb + OFF_F, g_tab + TAB_FG, 8192, bars + B_FG);
            wait_cnt(g_cnt, 128 * ep);
            STAMP(42);
            mbar_expect_tx(bars + B_UIN, 16384);
            bulk_ld(sb + OFF_P, usrc, 16384, bars + B_UIN);
            load_w_rows(sb + OFF_X, &tmWr, &tmWi, kap0, bars + B_WD);
            load_w_rows(sb + OFF_P + 16384, &tmWr, &tmWi, (512 - kap0) & 511, bars + B_WM);
            __nanosleep(1000);
            prefetch_w_rows(&tmWr, &tmWi, kap1);
            prefetch_w_rows(&tmWr, &tmWi, 512 - kap1);
            mbar_wait(bars + B_WFREE, 0);
            mbar_expect_tx(bars + B_UIN + 8, 16384);
            bulk_ld(sb + OFF_P + 16384, usrc + (extra ? 0 : 16384), 16384, bars + B_UIN + 8);
            load_w_rows(sb + OFF_X, &tmWr, &tmWi, kap1, bars + B_WD);
#pragma unroll 1
            for (int gi = 0; gi < 2; gi++) {
                mbar_wait(bars + B_STG, gi);
                STAMPR(23 + gi);
                if (extra ? (gi == 1) : (bid + gi != 0)) {
                    int cj;
                    const int s3 = extra ? 0 : slot3_of(gi ? kap1 : kap0, cj);
                    const uint32_t src = extra ? sb : sb + OFF_P + gi * 16384;
#pragma unroll 1
                    for (int r = 0; r < 256 / VBOX; r++) {
                        tma3d_st(&tmVst, s3 * 32, (r * VBOX) & 127, (r * VBOX) >> 7, src + r * (VBOX * 64));
                        if (r < 256 / VBOX - 1) __nanosleep(PACE_V);
                    }
                    bulk_commit();
                }
                if (gi == 0) { bulk_wait_read(); load_w_rows(sb + OFF_P, &tmWr, &tmWi, 512 - kap1, bars + B_WM); }
            }
            red_hint(g_cnt + 32);
            bulk_wait_read();
            STAMP(49);
            STAMP(43);
            if (!extra) {
                wait_cnt(g_cnt + 32, 129 * ep);
                STAMP(44);
                mbar_expect_tx(bars + B_VIN, 16384);
                bulk_ld(sb + OFF_P, g_V + (size_t)bid * 32768, 16384, bars + B_VIN);
                mbar_expect_tx(bars + B_VIN + 8, 16384);
                bulk_ld(sb + OFF_P + 16384, g_V + (size_t)bid * 32768 + 16384, 16384, bars + B_VIN + 8);
            }
          }
        } else {
            if (w == 2) {
            const int gi = lane >> 4, j = (lane >> 1) & 3, mir = (lane >> 3) & 1;
            const int kap = extra ? gi * 256 : kappa_of(bid * 2 + gi);
            const int r0 = kap + 512 * j, r1 = (2048 - r0) & 2047;
            const unsigned short* wp = (const unsigned short*)((lane & 1) ? p.wi : p.wr);
            const float a = bf2f(wp[r0 * 513 + mir * 512]), b = bf2f(wp[r1 * 513 + mir * 512]);
            asm volatile("st.shared.f32 [%0], %1;" ::"r"(sb + OFF_WSP + lane * 4), "f"(0.5f * ((lane & 1) ? a - b : a + b)) : "memory");
            __syncwarp();
            if (lane == 0) mbar_arrive(bars + B_WSP);
            }
            if (!extra) {
                const unsigned ep = get_epoch(bars);
                const uint32_t ca = sb + (q >> 1) * 8192 + (q & 1) * 512 + g * 1040 + q * 4, rb = bars + B_HR - 16 + w * 8;
                uint32_t rph = 0, hph = 0;
                int s = 32 % NST + w - 2, i5 = 0;
                const bool first = lane == 0;
#pragma unroll 1
                for (int kk = w - 2; kk < 32; kk += 2) {
                    mbar_wait(bars + B_HL - 16 + s * 16 + w * 8, hph);
#pragma unroll 1
                    for (int n = 0; n < 4096; n++) {
                        uint32_t v[4], ok;
#pragma unroll
                        for (int i = 0; i < 4; i++) asm volatile("ld.shared.u32 %0, [%1];" : "=r"(v[i]) : "r"(ca + s * 32768 + i * 128) : "memory");
                        asm volatile("{.reg .pred p; .reg .b32 a, b; lop3.b32 a, %1, %2, %5, 0x7e; lop3.b32 b, %3, %4, %5, 0x7e; lop3.b32 a, a, b, 1, 0xa8;\n"
                                     "setp.eq.u32 p, a, 0; vote.sync.all.pred p, p, -1; selp.u32 %0, 1, 0, p;}" : "=r"(ok) : "r"(v[0]), "r"(v[1]), "r"(v[2]), "r"(v[3]), "r"(ep));
                        if (ok) break;
                        int k2 = kk;
                        asm volatile("" : "+r"(k2));
                        if (elect_one()) { mbar_expect_tx(rb, 16384); bulk_ld(sb + s * 32768, g_H + (size_t)(tc * 32 + k2) * 16384, 16384, rb); }
                        mbar_wait(rb, rph);
                        rph ^= 1;
                    }
                    if (first) mbar_arrive(bars + B_FULL + s * 8);
                    s += 2;
                    if (s >= NST) s -= NST;
                    if (++i5 == NST) { i5 = 0; hph ^= 1; }
                }
            }
        }
    } else {
        asm volatile("barrier.cluster.arrive.relaxed.aligned; barrier.cluster.wait.aligned;" ::: "memory");
        STAMP(55);
        asm volatile("setmaxnreg.inc.sync.aligned.u32 152;");
        if (extra && (wg != 2 || bid == 129)) return;
        const int t7 = tid & 127, hf = wg - 1;
        const int k1 = 8 * w + g;
        const int mi = lane >> 3, gl = lane & 7;
        const uint32_t tmask = q == 0 ? ~1u : ~0u;
        if (wg != 0 && !extra) {
            uint32_t f1[16];
#pragma unroll
            for (int j = 0; j < 4; j++) { const uint4 v = ldtab(TAB_F1 + j * 512 + t7 * 4); f1[4 * j] = v.x; f1[4 * j + 1] = v.y; f1[4 * j + 2] = v.z; f1[4 * j + 3] = v.w; }
            cf tw[8];
            load_tw(tw, k1);
            const uint32_t tbit = get_epoch(bars) & ~tmask;
            float acc[64];
            const uint64_t dx = opaque(mkdesc(sb + OFF_F + hf * 16384, 2048, 256, 3));
            mbar_wait(bars + B_XIN + hf * 8, 0);
            STAMP(20);
            pinu(f1);
            wg_fence();
#pragma unroll
            for (int j = 0; j < 4; j++)
                mma128_rs<1>(acc, f1[4 * j], f1[4 * j + 1], f1[4 * j + 2], f1[4 * j + 3], dx + j * 32, j);
            wg_commit();
            wg_wait<0>();
            pin(acc);
            pinu(f1);
            if (hf == 0) bar_sync(8, 128);
            else bar_sync(3, 128);
            if (k1 == 0) {
#pragma unroll
                for (int i = 0; i < 16; i++) {
                    const uint32_t a = sb + OFF_F + hf * 16384 + (i >> 1) * 64 + ((i & 1) * 8 + 2 * q) * 4;
                    sts64f(a, acc[4 * i], acc[4 * i + 1]);
                    sts64f(a + 512, acc[4 * i + 2], acc[4 * i + 3]);
                }
            }
            uint4 fx0, fx1;
#pragma unroll
            for (int cl = 0; cl < 2; cl++) {
                if (cl == 1) {
                    asm volatile("ld.global.nc.v4.b32 {%0,%1,%2,%3}, [%4];" : "=r"(fx0.x), "=r"(fx0.y), "=r"(fx0.z), "=r"(fx0.w) : "l"(g_tab + TAB_FX + ((t7 >> 2) & 15) * 8));
                    asm volatile("ld.global.nc.v4.b32 {%0,%1,%2,%3}, [%4];" : "=r"(fx1.x), "=r"(fx1.y), "=r"(fx1.z), "=r"(fx1.w) : "l"(g_tab + TAB_FX + ((t7 >> 2) & 15) * 8 + 4));
                }
                cf v0[8], v1[8];
#pragma unroll
                for (int n = 0; n < 8; n++) {
                    const int i = 4 * (2 * n + cl);
                    v0[n] = {acc[i], acc[i + 2]};
                    v1[n] = {acc[i + 1], acc[i + 3]};
                }
                dft8<true>(v0, tw);
                dft8<true>(v1, tw);
                const uint32_t a0 = sb + OFF_P + (8 * w + gl + 32 * (mi >> 1)) * 128 + (((((mi & 1) << 2) | ((2 * hf + cl) ^ (fpos & 3))) ^ gl) << 4);
#pragma unroll
                for (int r = 0; r < 8; r += 2) {
                    uint32_t o0 = pk(v0[r].x, v1[r].x), o1 = pk(v0[r].y, v1[r].y), o2 = pk(v0[r + 1].x, v1[r + 1].x), o3 = pk(v0[r + 1].y, v1[r + 1].y);
                    if (cl == 0) { o0 = (o0 & tmask) | tbit; o1 = (o1 & tmask) | tbit; o2 = (o2 & tmask) | tbit; o3 = (o3 & tmask) | tbit; }
                    stsm4(a0 + r * 4096, o0, o1, o2, o3);
                }
            }
            if (hf == 0) bar_sync(8, 128);
            else bar_sync(3, 128);
            if (t7 & 64) {
                const int o = (t7 >> 2) & 15, r = o >> 1, ri = o & 1, cg = t7 & 3;
                float s0 = 0.f, s1 = 0.f, s2 = 0.f, s3 = 0.f;
#pragma unroll
                for (int n = 0; n < 8; n++) {
                    const float c = __uint_as_float(n < 4 ? (n == 0 ? fx0.x : n == 1 ? fx0.y : n == 2 ? fx0.z : fx0.w) : (n == 4 ? fx1.x : n == 5 ? fx1.y : n == 6 ? fx1.z : fx1.w));
                    float x0, x1, x2, x3;
                    lds128f(sb + OFF_F + hf * 16384 + (r < 4 ? 0 : 512) + n * 64 + cg * 16, x0, x1, x2, x3);
                    s0 = fmaf(c, x0, s0); s1 = fmaf(c, x1, s1); s2 = fmaf(c, x2, s2); s3 = fmaf(c, x3, s3);
                }
                asm volatile("st.shared.v2.b32 [%0], {%1,%2};" ::"r"(sb + OFF_P + r * 4096 + ((ri * 4 + ((2 * hf + (cg >> 1)) ^ (fpos & 3))) << 4) + (cg & 1) * 8), "r"((pk(s0, s1) & tmask) | tbit), "r"(pk(s2, s3)) : "memory");
            }
            fence_async_sm();
            __syncwarp();
            if (lane == 0) mbar_arrive(bars + B_STGU);
        }
        if (wg != 2) {
        if (wg == 0) bar_sync(4, 128);
        asm volatile("setmaxnreg.inc.sync.aligned.u32 168;");
        const int ch0 = wg * 512 + cb * 64;
        if (wg == 1) {
            const int cl = tid & 127, ch = (cl >> 6) * 512 + ((cl >> 3) & 1) * 256 + cb * 32 + ((cl >> 4) & 3) * 8 + (cl & 7);
            const float lr = __bfloat162float(p.lre[ch]), li = __bfloat162float(p.lim[ch]);
            const float dt = __bfloat162float(__float2bfloat16(expf(__bfloat162float(p.ldt[ch]))));
            float sn, cs;
            sincosf(dt * li, &sn, &cs);
            const float ex = expf(dt * lr), br = ex * cs, bi = ex * sn;
            const float inv = 2.0f / (lr * lr + li * li);
            const float cr = ((br - 1.f) * lr + bi * li) * inv, ci = (bi * lr - (br - 1.f) * li) * inv;
            sts128(sb + OFF_LAM + cl * 16, __float_as_uint(br), __float_as_uint(-bi), __float_as_uint(cr), __float_as_uint(-ci));
            mbar_wait(bars + B_EP, 0);
            __syncwarp();
            if (lane == 0) mbar_arrive(bars + B_LAM);
        }
        float d[128];
        if (wg == 1) bar_sync(1, 256);
        STAMPW(0, 10);
        Ring rg = ring_at(sb, wg * 16);
        cf lam[2], M[2];
        unsigned ep;
        const uint32_t lama = sb + OFF_LAM + wg * 1024 + (16 * w + g) * 16;
        auto hook = [&]() {
            mbar_wait_fast(bars + B_LAM, 0);
            lam[0] = lds_cf(lama); lam[1] = lds_cf(lama + 128);
            M[0] = lds_cf(lama + ((lane & 7) - g) * 16); M[1] = lds_cf(lama + ((lane & 7) - g) * 16 + 128);
            asm volatile("ld.shared.u32 %0, [%1];" : "=r"(ep) : "r"(bars + B_EPOCH) : "memory");
        };
        if (wg == 0) gemm1<0>(d, rg, hook); else gemm1<16>(d, rg, hook);
        cf L[2] = {lam[0], lam[1]};
#pragma unroll
        for (int i = 0; i < 7; i++) {
            M[0] = csq(M[0]); M[1] = csq(M[1]);
            if (i < 4) { L[0] = csq(L[0]); L[1] = csq(L[1]); }
            YIELD();
        }
        asm volatile("" : "+f"(M[0].x), "+f"(M[0].y), "+f"(M[1].x), "+f"(M[1].y), "+f"(L[0].x), "+f"(L[0].y), "+f"(L[1].x), "+f"(L[1].y)::"memory");
        wg_wait<0>();
        ring_release(rg, wg ? SL(31) : SL(15));
        pin(d);
        STAMPW(1, 11);
        {
            cf f[2], fb2[2];
#pragma unroll
            for (int i = 0; i < 17; i++) {
#pragma unroll
                for (int h = 0; h < 2; h++) {
                    const int r = 4 * (i >> 1) + 2 * h + (i & 1), r2 = 32 + 4 * ((i - 1) >> 1) + 2 * h + ((i - 1) & 1);
                    if (i < 16) f[h] = i ? cfma(lam[h], f[h], {d[r], -d[64 + r]}) : cf{d[r], -d[64 + r]};
                    if (i > 0) fb2[h] = i > 1 ? cfma(lam[h], fb2[h], {d[r2], -d[64 + r2]}) : cf{d[r2], -d[64 + r2]};
                    if (i && (h || !(YS & 8))) YIELD_S1();
                }
            }
            cf st[2];
            uint4* cbase = g_carry + (ch0 >> 1) + 8 * w;
            const unsigned tag = ep & 15u;
#pragma unroll
            for (int h = 0; h < 2; h++) { f[h] = cfma(L[h], f[h], fb2[h]); L[h] = csq(L[h]); }
            cf s0[2], s1[2], s2[2];
#pragma unroll
            for (int h = 0; h < 2; h++) {
                s0[h] = {__shfl_sync(~0u, f[h].x, 0, 4), __shfl_sync(~0u, f[h].y, 0, 4)};
                s1[h] = {__shfl_sync(~0u, f[h].x, 1, 4), __shfl_sync(~0u, f[h].y, 1, 4)};
                s2[h] = {__shfl_sync(~0u, f[h].x, 2, 4), __shfl_sync(~0u, f[h].y, 2, 4)};
            }
#pragma unroll
            for (int h = 0; h < 2; h++) {
                s1[h] = cfma(L[h], s0[h], s1[h]);
                s2[h] = cfma(L[h], s1[h], s2[h]);
                f[h] = cfma(L[h], s2[h], f[h]);
            }
            if (q == 3)
                asm volatile("{.reg .b64 a, b; mov.b64 a, {%1,%2}; mov.b64 b, {%3,%4}; st.relaxed.gpu.global.v2.b64 [%0], {a, b};}" ::"l"(cbase + g + tc * 512),
                             "r"((__float_as_uint(f[0].x) & ~15u) | tag), "f"(f[0].y), "r"((__float_as_uint(f[1].x) & ~15u) | tag), "f"(f[1].y) : "memory");
            STAMPX(2, 12);
            cf gam[2] = {lds_cf(lama + 8), lds_cf(lama + 136)};
            cf lq[2], Mw[2];
#pragma unroll
            for (int h = 0; h < 2; h++) {
                const cf one = {1.f, 0.f}, L2 = csq(L[h]), M2 = csq(M[h]);
                st[h] = (q & 2) ? ((q & 1) ? s2[h] : s1[h]) : ((q & 1) ? s0[h] : cf{0.f, 0.f});
                YIELD();
                lq[h] = cmul((q & 1) ? L[h] : one, (q & 2) ? L2 : one);
                YIELD();
                Mw[h] = cmul((lane & 8) ? M[h] : one, (lane & 16) ? M2 : one);
                M[h] = csq(M2);
                YIELD();
            }
#pragma unroll
            for (int h = 0; h < 2; h++) { st[h] = cmul(gam[h], st[h]); lq[h] = cmul(gam[h], lq[h]); YIELD(); }
            prescale<0>(d, gam[0]);
            {
                uint32_t fv[4][4];
                unsigned n = 0;
                bool ok;
                do {
                    asm volatile(
                        "{.reg .pred p0, p1, p2, p3; .reg .b64 a0, b0, a1, b1, a2, b2, a3, b3;\n"
                        "setp.ge.s32 p0, %17, 0; setp.ge.s32 p1, %17, 4; setp.ge.s32 p2, %17, 8; setp.ge.s32 p3, %17, 12;\n"
                        "mov.b64 a0, {%18,%18}; mov.b64 b0, a0; mov.b64 a1, a0; mov.b64 b1, a0; mov.b64 a2, a0; mov.b64 b2, a0; mov.b64 a3, a0; mov.b64 b3, a0;\n"
                        "@p0 ld.relaxed.gpu.global.v2.b64 {a0, b0}, [%16];\n"
                        "@p1 ld.relaxed.gpu.global.v2.b64 {a1, b1}, [%16+-32768];\n"
                        "@p2 ld.relaxed.gpu.global.v2.b64 {a2, b2}, [%16+-65536];\n"
                        "@p3 ld.relaxed.gpu.global.v2.b64 {a3, b3}, [%16+-98304];\n"
                        "mov.b64 {%0,%1}, a0; mov.b64 {%2,%3}, b0; mov.b64 {%4,%5}, a1; mov.b64 {%6,%7}, b1;\n"
                        "mov.b64 {%8,%9}, a2; mov.b64 {%10,%11}, b2; mov.b64 {%12,%13}, a3; mov.b64 {%14,%15}, b3;}"
                        : "=r"(fv[0][0]), "=r"(fv[0][1]), "=r"(fv[0][2]), "=r"(fv[0][3]), "=r"(fv[1][0]), "=r"(fv[1][1]), "=r"(fv[1][2]), "=r"(fv[1][3]),
                          "=r"(fv[2][0]), "=r"(fv[2][1]), "=r"(fv[2][2]), "=r"(fv[2][3]), "=r"(fv[3][0]), "=r"(fv[3][1]), "=r"(fv[3][2]), "=r"(fv[3][3])
                        : "l"(cbase + (lane & 7) + (tc - 1 - (lane >> 3)) * 512), "r"(tc - 1 - (lane >> 3)), "r"(tag) : "memory");
                    unsigned bad = 0;
#pragma unroll
                    for (int a = 0; a < 8; a++) bad |= fv[a >> 1][2 * (a & 1)] ^ tag;
                    ok = (bad & 15u) == 0;
                } while (!__all_sync(~0u, ok) && ++n < SPIN_LIMIT);
                STAMPX(53, 54);
                cf P[2];
#pragma unroll
                for (int h = 0; h < 2; h++) P[h] = {__uint_as_float(fv[3][2 * h]), __uint_as_float(fv[3][2 * h + 1])};
#pragma unroll
                for (int a = 2; a >= 0; a--)
#pragma unroll
                    for (int h = 0; h < 2; h++) P[h] = cfma(M[h], P[h], {__uint_as_float(fv[a][2 * h]), __uint_as_float(fv[a][2 * h + 1])});
                lam[0] = lds_cf(lama); lam[1] = lds_cf(lama + 128);
#pragma unroll
                for (int h = 0; h < 2; h++) P[h] = cmul(P[h], Mw[h]);
                float sx[2][4], sy[2][4];
#pragma unroll
                for (int h = 0; h < 2; h++)
#pragma unroll
                    for (int j = 0; j < 4; j++) { sx[h][j] = __shfl_sync(~0u, P[h].x, g + 8 * j); sy[h][j] = __shfl_sync(~0u, P[h].y, g + 8 * j); }
#pragma unroll
                for (int h = 0; h < 2; h++) st[h] = cfma(lq[h], {(sx[h][0] + sx[h][1]) + (sx[h][2] + sx[h][3]), (sy[h][0] + sy[h][1]) + (sy[h][2] + sy[h][3])}, st[h]);
            }
            STAMPX(3, 13);
            uint8_t* hptr = g_H + (size_t)(tc * 32 + wg * 16 + (cb & 6)) * 16384 + ((cb & 1) * 4 + w) * 1024 + g * 64 + ((q ^ (g >> 1)) << 4);
            const bool tg = 4 * (g & 1) + (q ^ (g >> 1)) == (cb & 1) * 4 + w;
            const uint32_t hm = tg ? ~1u : ~0u, hb = ep & ~hm;
            uint32_t keep = sb >> 28;
            scan2<0>(d, lam[0], st[0], hptr, hm, hb, keep);
            __syncwarp();
            if (lane == 0) mbar_arrive(bars + B_HOWN + wg * 16);
            STAMPW(4, 14);
            prescale<1>(d, lds_cf(lama + 136));
            STAMPW(51, 52);
            scan2<1>(d, lam[1], st[1], hptr + 8 * 16384, hm, hb, keep);
            __syncwarp();
            if (lane == 0) mbar_arrive(bars + B_HOWN + wg * 16 + 8 + keep);
            STAMPW(5, 15);
        }
        if (wg == 0) {
            float y[128];
            uint32_t dd[16];
            const uint8_t* dp = (const uint8_t*)(p.dsk + cb * 128) + opaque32(q * 8);
#pragma unroll
            for (int i = 0; i < 8; i++) asm volatile("ld.global.nc.v2.b32 {%0,%1}, [%2];" : "=r"(dd[2 * i]), "=r"(dd[2 * i + 1]) : "l"(dp + 32 * i));
            const int pg = 2 * (g & 3) + (g >> 2);
            float* op = (float*)((uint8_t*)(p.out + (size_t)(tc * 128 + 64 * (w & 1) + 8 * (w >> 1)) * 2048 + 1024 + cb * 128) + opaque32(pg * 8192 + q * 16));
            const uint32_t xa = sb + OFF_F + (16 * (w & 1) + 8 * (w >> 1) + pg) * 128 + (((q >> 1) ^ pg) << 4) + (q & 1) * 8;
            rg = ring_at(sb, 32);
            pinu(dd);
            STAMP(6);
            bar_sync(2, 256);
            STAMP(7);
            mbar_wait_fast(rg.full + SL(32) * 8, PH(32));
            gemm_step<1, 0, 32, 0>(y, rg, 0, false);
#pragma unroll 1
            for (int it = 0;; it++) {
                const uint32_t f = it & 1;
                gemm_step<1, 1, 33, 0>(y, rg, f, true);
                if (SKEW == 5 && it == 5) break;
                gemm_step<1, 1, 34, 0>(y, rg, f, true);
                if (SKEW == 4 && it == 5) break;
                gemm_step<1, 1, 35, 0>(y, rg, f, it != 5);
                if (SKEW == 3 && it == 5) break;
                gemm_step<1, 1, 36, 0>(y, rg, f, it != 5);
                if (SKEW == 2 && it == 5) break;
                gemm_step<1, 1, 37, 0>(y, rg, f, true);
            }
#define HALF0(k) if (64 - SKEW <= k) { wg_fence(); if (k < 63) peek(rg.full + SL(k + 1) * 8, PH(k + 1)); else peek(bars + B_XD, 0); half_step<0, k>(y); \
                  if (k == 59) { wg_commit(); wg_wait<1>(); ring_release(rg, SL(58)); } if (k < 63) peek_wait(rg.full + SL(k + 1) * 8, PH(k + 1)); }
            HALF0(59) HALF0(60) HALF0(61) HALF0(62) HALF0(63)
            wg_commit();
            peek_wait(bars + B_XD, 0);
            uint32_t xa0[8], xa1[8];
            load_x4<0, 0>(xa0, xa);
            wg_fence();
            half_step<64, 64 - SKEW>(y);
            wg_commit();
            wg_wait<1>();
#pragma unroll
            for (int i = 0; i < 64; i++) asm volatile("" : "+f"(y[i])::"memory");
            STAMP(16);
#define MM(n) if (4 + (n) < 4 * SKEW) { wg_fence(); mma_h<64, 65 - SKEW + (n) / 4, (n) % 4>(y); mma_h<64, 65 - SKEW + (n) / 4, (n) % 4 + 1>(y); }
#define OUT4(R, U, X, n) out_piece<R, U>(y, dd, X[0], X[1], op); MM(n) out_piece<R, U + 1>(y, dd, X[2], X[3], op); MM(n + 2) \
                         out_piece<R, U + 2>(y, dd, X[4], X[5], op); MM(n + 4) out_piece<R, U + 3>(y, dd, X[6], X[7], op); MM(n + 6)
            load_x4<0, 4>(xa1, xa);
            OUT4(0, 0, xa0, 0)
            load_x4<1, 0>(xa0, xa);
            OUT4(0, 4, xa1, 8)
            wg_commit();
            load_x4<1, 4>(xa1, xa);
            OUT4(1, 0, xa0, 16)
            load_x4<2, 0>(xa0, xa);
            OUT4(1, 4, xa1, 16)
            STAMP(18);
            wg_wait<0>();
#pragma unroll
            for (int i = 64; i < 128; i++) asm volatile("" : "+f"(y[i])::"memory");
            STAMP(8);
            load_x4<2, 4>(xa1, xa);
            mbar_wait_fast(bars + B_XD + 8, 0);
            OUT4(2, 0, xa0, 16)
            load_x4<3, 0>(xa0, xa);
            OUT4(2, 4, xa1, 16)
            load_x4<3, 4>(xa1, xa);
            OUT4(3, 0, xa0, 16)
            OUT4(3, 4, xa1, 16)
            STAMP(9);
            return;
        }
        bar_sync(8, 128);
        asm volatile("setmaxnreg.dec.sync.aligned.u32 152;");
        } else {
        {
            cf T[8];
            load_T(T, t7);
            const uint32_t tag = get_epoch(bars) & 1;
            mbar_wait(bars + B_WSP, 0);
            mbar_wait(bars + B_FG, 0);
#pragma unroll 1
            for (int gi = 0; gi < 2; gi++) {
                const int kap = extra ? gi * 256 : kappa_of(bid * 2 + gi);
                const uint32_t buf = sb + OFF_P + gi * 16384;
                STAMP3(39);
                const int kq = kap + 512 * q;
                const cf be1 = twid(kq, 2048), be2 = cmul(be1, be1), be3 = cmul(be1, be2);
                uint32_t wad[4];
#pragma unroll
                for (int j = 0; j < 4; j++) wad[j] = sb + OFF_X + ((j + q) & 3) * WPITCH + ((2 * kap) & 15) + 2 * k1 + 128 * q;
                float acc[64], za[32], zb[32], ya[32], yb[32], vv[64];
                const uint64_t dF = opaque(mkdesc(sb + OFF_F, 16, 1024, 1)), dB = opaque(mkdesc(buf, 4096, 512, 2));
#pragma unroll 1
                for (int n = 0; n < 4096; n++) {
                    mbar_wait(bars + B_UIN + gi * 8, n & 1);
                    STAMP3(22);
                    wg_fence();
#pragma unroll
                    for (int j = 0; j < 4; j++) mma128_ss<0, 0, 1>(acc, dF + j * 2, dB + j * 64, j);
                    wg_commit();
                    const uint32_t bad = tags_bad<4>(buf, tag, t7);
                    wg_wait<0>();
                    pin(acc);
                    if (wg_all_ok(bad, 3)) break;
                    if (t7 == 0) { mbar_expect_tx(bars + B_UIN + gi * 8, 16384); bulk_ld(buf, g_U + (size_t)(extra ? 0 : bid * 2 + gi) * 16384, 16384, bars + B_UIN + gi * 8); }
                }
                STAMP3(30);
                uint32_t af[32];
#pragma unroll
                for (int b = 0; b < 4; b++)
#pragma unroll
                    for (int c = 0; c < 4; c++) {
                        const int i = 4 * (4 * b + c);
                        cf x0 = cmul({acc[i], acc[i + 2]}, T[2 * c]), x1 = cmul({acc[i + 1], acc[i + 3]}, T[2 * c + 1]);
                        af[16 * (b >> 1) + 4 * c + (b & 1)] = pk(x0.x, x0.y);
                        af[16 * (b >> 1) + 4 * c + 2 + (b & 1)] = pk(x1.x, x1.y);
                    }
                pinu(af);
                wg_fence();
#pragma unroll
                for (int j = 0; j < 4; j++) {
                    const uint64_t db = dF + j * 2;
                    mma64_rs<0>(za, af[4 * j], af[4 * j + 1], af[4 * j + 2], af[4 * j + 3], db, j);
                    mma64_rs<0>(zb, af[16 + 4 * j], af[17 + 4 * j], af[18 + 4 * j], af[19 + 4 * j], db, j);
                }
                wg_commit();
                STAMP3(31);
                mbar_wait(bars + B_WD, gi);
                cf W0[8];
#pragma unroll
                for (int i = 0; i < 8; i++) W0[i] = {lds_bf(wad[i & 3] + 64 * (i >> 2)), lds_bf(wad[i & 3] + 64 * (i >> 2) + 4 * WPITCH)};
                wg_wait<0>();
                pin(za);
                pin(zb);
                pinu(af);
                STAMP3(32);
#pragma unroll
                for (int jb = 0; jb < 4; jb++) {
                    if (jb == 2) {
                        STAMP3(37);
                        mbar_wait(bars + B_WM, gi);
#pragma unroll
                        for (int j = 0; j < 4; j++)
                            wad[j] = sb + OFF_P + (gi ^ 1) * 16384 + (((kap ? 3 : 4) - j - q) & 3) * WPITCH + ((-2 * kap) & 15) + 1024 - 2 * k1 - 128 * q;
                    }
                    if (jb == 3) load_T(T, t7);
                    cf z[2][4];
#pragma unroll
                    for (int e = 0; e < 2; e++) {
                        cf W[4];
#pragma unroll
                        for (int j = 0; j < 4; j++) {
                            const int off = jb < 2 ? 512 * jb + 64 * e : -(512 * (jb - 2) + 64 * e);
                            if (jb == 0) W[j] = W0[4 * e + j];
                            else W[j] = {lds_bf(wad[j] + off), lds_bf(wad[j] + off + 4 * WPITCH)};
                            if (jb >= 2) W[j].y = -W[j].y;
                        }
                        if ((jb & 1) == 0 && e == 0 && t7 == 0) {
                            lds128f(sb + OFF_WSP + gi * 64 + jb * 16, W[0].x, W[0].y, W[1].x, W[1].y);
                            lds128f(sb + OFF_WSP + gi * 64 + jb * 16 + 16, W[2].x, W[2].y, W[3].x, W[3].y);
                        }
                        const int i = 8 * jb + e;
                        const cf z0 = {za[i], za[i + 4]}, z1 = cmul({za[i + 2], za[i + 6]}, be1);
                        cf s0 = cfma({zb[i], zb[i + 4]}, be2, z0), s1 = twice_minus(z0, s0);
                        cf s2 = cfma({zb[i + 2], zb[i + 6]}, be3, z1), s3 = twice_minus(z1, s2);
                        const cf y0 = cmul(cadd(s0, s2), W[0]), y1 = cmul({s1.x + s3.y, s1.y - s3.x}, W[1]);
                        const cf x2 = csub(s0, s2), x3 = {s1.x - s3.y, s1.y + s3.x};
                        s0 = cfma(x2, W[2], y0); s1 = twice_minus(y0, s0);
                        s2 = cfma(x3, W[3], y1); s3 = twice_minus(y1, s2);
                        z[e][0] = cadd(s0, s2);
                        z[e][2] = cmulc(csub(s0, s2), be2);
                        z[e][1] = cmulc({s1.x - s3.y, s1.y + s3.x}, be1);
                        z[e][3] = cmulc({s1.x + s3.y, s1.y - s3.x}, be3);
                    }
#pragma unroll
                    for (int b = 0; b < 4; b++) {
                        af[16 * (b >> 1) + 4 * jb + (b & 1)] = pk(z[0][b].x, z[1][b].x);
                        af[16 * (b >> 1) + 4 * jb + 2 + (b & 1)] = pk(z[0][b].y, z[1][b].y);
                    }
                }
                pinu(af);
                __syncwarp();
                if (lane == 0) mbar_arrive(bars + B_WFREE);
                wg_fence();
#pragma unroll
                for (int j = 0; j < 4; j++) {
                    const uint64_t db = dF + j * 128;
                    mma64_rs<1>(ya, af[4 * j], af[4 * j + 1], af[4 * j + 2], af[4 * j + 3], db, j);
                    mma64_rs<1>(yb, af[16 + 4 * j], af[17 + 4 * j], af[18 + 4 * j], af[19 + 4 * j], db, j);
                }
                wg_commit();
                STAMP3(33);
                wg_wait<0>();
                STAMP3(34);
                pin(ya);
                pin(yb);
                pinu(af);
                {
                    const uint32_t a0 = buf + (mi & 1) * 4096 + (16 * w + 8 * (mi >> 1) + gl) * 64;
#pragma unroll
                    for (int u = 0; u < 2; u++)
#pragma unroll
                        for (int c = 0; c < 4; c++) {
                            const int i = 8 * c;
                            const float(&yy)[32] = u ? yb : ya;
                            cf x0 = cmulc({yy[i], yy[i + 1]}, T[2 * c]), x1 = cmulc({yy[i + 4], yy[i + 5]}, T[2 * c + 1]);
                            cf y0 = cmulc({yy[i + 2], yy[i + 3]}, T[2 * c]), y1 = cmulc({yy[i + 6], yy[i + 7]}, T[2 * c + 1]);
                            stsm4(a0 + u * 8192 + ((c ^ (gl >> 1)) << 4), pk(x0.x, x1.x), pk(y0.x, y1.x), pk(x0.y, x1.y), pk(y0.y, y1.y));
                        }
                }
                STAMP3(38);
                fence_async_sm();
                bar_sync(3, 128);
                wg_fence();
#pragma unroll
                for (int j = 0; j < 4; j++) mma128_ss<0, 1, 1>(vv, dF + j * 128, dB + j * 64, j);
                wg_commit();
                STAMP3(35);
                int cj = 0, s3 = 0;
                if (!extra) s3 = slot3_of(kap, cj);
                const uint32_t flip = ((g & 1) && !cj) ? 0x80008000u : 0u, flipt = flip | (tag & ~tmask);
                wg_wait<0>();
                pin(vv);
                STAMP3(36);
                bar_sync(3, 128);
                {
                    const int rw = 8 * w + (gl & 6) + (mi & 1);
                    const uint32_t a0 = (extra ? ((gl & 1) == gi ? sb : sb + 16384) : buf) + rw * 64 +
                                        (((((gl & 1) << 1) | ((mi >> 1) ^ ((s3 >> 1) & 1))) ^ ((rw >> 1) & 3)) << 4);
#pragma unroll
                    for (int b = 0; b < 4; b++)
#pragma unroll
                        for (int c = 0; c < 4; c += 2) {
                            const int i = 4 * (4 * b + c);
                            stsm4(a0 + b * 2048 + c * 4096, (pk(vv[i], vv[i + 1]) & tmask) ^ flipt, (pk(vv[i + 2], vv[i + 3]) & tmask) ^ flipt,
                                  pk(vv[i + 4], vv[i + 5]) ^ flip, pk(vv[i + 6], vv[i + 7]) ^ flip);
                        }
                }
                fence_async_sm();
                __syncwarp();
                if (lane == 0) mbar_arrive(bars + B_STG);

            }
        }
        if (extra) return;
        }
        {
            uint32_t sp[8];
#pragma unroll
            for (int j = 0; j < 2; j++) { const uint4 v = ldtab(TAB_SP + j * 512 + t7 * 4); sp[4 * j] = v.x; sp[4 * j + 1] = v.y; sp[4 * j + 2] = v.z; sp[4 * j + 3] = v.w; }
            cf tw[8];
            load_tw(tw, k1);
            tw[4].x *= 2.f; tw[4].y *= 2.f;
            const uint32_t tag = get_epoch(bars) & 1;
            const uint32_t in = sb + OFF_P + hf * 16384;
            const uint64_t dF = opaque(mkdesc(sb + OFF_F, 16, 1024, 1)), dB = opaque(mkdesc(in, 2048, 256, 3));
            float acc[64];
#pragma unroll 1
            for (int n = 0; n < 4096; n++) {
                mbar_wait(bars + B_VIN + hf * 8, n & 1);
                STAMP(25);
                pinu(sp);
                wg_fence();
#pragma unroll
                for (int j = 0; j < 4; j++) {
                    mma112_ss(acc, dF + j * 2, dB + 128 + j * 32, j);
                    if (j < 2) mma16_rs(acc, sp[2 * j], 0u, sp[2 * j + 1], 0u, dB + j * 32, j);
                    else mma16_rs(acc, 0u, sp[2 * j], 0u, sp[2 * j + 1], dB + j * 32, 1);
                }
                wg_commit();
                const uint32_t bad = tags_bad<4>(in, tag, t7);
                wg_wait<0>();
                pin(acc);
                pinu(sp);
                if (wg_all_ok(bad, hf ? 3 : 8)) break;
                if (t7 == 0) { mbar_expect_tx(bars + B_VIN + hf * 8, 16384); bulk_ld(in, g_V + (size_t)bid * 32768 + hf * 16384, 16384, bars + B_VIN + hf * 8); }
            }
            uint32_t o[2][16];
#pragma unroll
            for (int cl = 0; cl < 2; cl++) {
                cf z[2][8];
#pragma unroll
                for (int e = 0; e < 2; e++) {
                    const float b0 = acc[4 * cl + e], b8 = acc[4 * cl + 2 + e];
                    z[e][0] = {b0 + b8, b0 - b8};
                    z[e][4] = cmul({acc[4 * (8 + cl) + e], acc[4 * (8 + cl) + 2 + e]}, tw[4]);
#pragma unroll
                    for (int n = 1; n < 4; n++) {
                        const cf w16 = n == 1 ? cf{0.92387953251128674f, -0.38268343236508977f}
                                              : (n == 2 ? cf{0.70710678118654752f, -0.70710678118654752f} : cf{0.38268343236508977f, -0.92387953251128674f});
                        const cf y = cmul({acc[4 * (2 * n + cl) + e], acc[4 * (2 * n + cl) + 2 + e]}, tw[n]);
                        const cf u = {acc[4 * (2 * (8 - n) + cl) + e], acc[4 * (2 * (8 - n) + cl) + 2 + e]}, t = tw[8 - n];
                        const cf E = {fmaf(u.x, t.x, fmaf(-u.y, t.y, y.x)), fmaf(-u.x, t.y, fmaf(-u.y, t.x, y.y))};
                        const cf D = twice_minus(y, E);
                        z[e][n] = {fmaf(-D.x, w16.y, fmaf(-D.y, w16.x, E.x)), fmaf(D.x, w16.x, fmaf(-D.y, w16.y, E.y))};
                        z[e][8 - n] = {fmaf(2.f, E.x, -z[e][n].x), fmaf(-2.f, E.y, z[e][n].y)};
                    }
                    dft8<false>(z[e], tw);
                }
#pragma unroll
                for (int m = 0; m < 8; m++) { o[cl][2 * m] = pk(z[0][m].x, z[1][m].x); o[cl][2 * m + 1] = pk(z[0][m].y, z[1][m].y); }
            }
            const uint32_t a0 = in + (8 * w + gl + 32 * (mi >> 1)) * 32 + (((mi & 1) ^ (gl >> 2)) << 4);
#pragma unroll
            for (int m = 0; m < 16; m += 2) stsm4(a0 + m * 1024, o[0][m], o[1][m], o[0][m + 1], o[1][m + 1]);
            bar_sync(7, 256);
            STAMP(26);
            const int l8 = lane & 7, n0 = 16 * hf + 4 * w + mi;
            const uint32_t la = sb + OFF_P + (l8 >> 2) * 16384 + n0 * 32 + ((((l8 >> 1) & 1) ^ (w & 1)) << 4) + (l8 & 1) * 8;
            float* op = p.out + (size_t)(4 * n0 + fb) * 2048 + fcb * 32 + l8 * 4;
#pragma unroll 1
            for (int it = 0; it < 16; it += 4) {
                uint32_t u[8], fast;
                asm volatile("{.reg .pred p; mbarrier.test_wait.parity.shared::cta.b64 p, [%1], 0; selp.u32 %0, 1, 0, p;}" : "=r"(fast) : "r"(bars + B_LDONE) : "memory");
#pragma unroll
                for (int i = 0; i < 4; i++) asm volatile("ld.shared.v2.b32 {%0,%1}, [%2];" : "=r"(u[2 * i]), "=r"(u[2 * i + 1]) : "r"(la + (it + i) * 1024) : "memory");
#pragma unroll
                for (int i = 0; i < 4; i++) {
                    asm volatile("st.global.v4.b32 [%0], {%1,%2,%3,%4};" ::"l"(op + (size_t)(it + i) * 128 * 2048), "r"(u[2 * i] << 16), "r"(u[2 * i] & 0xffff0000u), "r"(u[2 * i + 1] << 16), "r"(u[2 * i + 1] & 0xffff0000u) : "memory");
                    if (!fast) __nanosleep(PACE_O);
                }
            }
            STAMP(27);
        }
    }
}

typedef CUresult (*EncodeFn)(CUtensorMap*, CUtensorMapDataType, cuuint32_t, void*, const cuuint64_t*, const cuuint64_t*, const cuuint32_t*,
                             const cuuint32_t*, CUtensorMapInterleave, CUtensorMapSwizzle, CUtensorMapL2promotion, CUtensorMapFloatOOBfill);

static CUtensorMap make_map(EncodeFn enc, const void* ptr, int rank, const cuuint64_t* dims, const cuuint64_t* strides, const cuuint32_t* box,
                            CUtensorMapSwizzle swz, CUtensorMapL2promotion promo, CUtensorMapDataType dt = CU_TENSOR_MAP_DATA_TYPE_BFLOAT16) {
    CUtensorMap m;
    const cuuint32_t es[5] = {1, 1, 1, 1, 1};
    enc(&m, dt, rank, const_cast<void*>(ptr), dims, strides, box, es, CU_TENSOR_MAP_INTERLEAVE_NONE, swz, promo,
        CU_TENSOR_MAP_FLOAT_OOB_FILL_NONE);
    return m;
}

extern "C" void kernel_launch(void* const* d_in, const int* in_sizes, int n_in, void* d_out, int out_size) {
    void* fn = nullptr;
    cudaDriverEntryPointQueryResult qr;
    cudaGetDriverEntryPoint("cuTensorMapEncodeTiled", &fn, cudaEnableDefault, &qr);
    EncodeFn enc = (EncodeFn)fn;
    void *pU, *pV;
    cudaGetSymbolAddress(&pU, g_U);
    cudaGetSymbolAddress(&pV, g_V);
    const CUtensorMapL2promotion P256 = CU_TENSOR_MAP_L2_PROMOTION_L2_256B, P0 = CU_TENSOR_MAP_L2_PROMOTION_NONE;

    const cuuint64_t dX[5] = {1024, 2, 4, 16, 16}, sX[4] = {2048, 32 * 2048, 2 * 2048, 128 * 2048};
    const cuuint32_t bX[5] = {64, 2, 4, 16, 1};
    CUtensorMap tmX = make_map(enc, d_in[3], 5, dX, sX, bX, CU_TENSOR_MAP_SWIZZLE_128B, P256);
    const cuuint64_t dXd[4] = {64, 2048, 2, 16}, sXd[3] = {2048, 64 * 2048, 128};
    const cuuint32_t bXd[4] = {64, 16, 2, 2};
    CUtensorMap tmXd = make_map(enc, d_in[3], 4, dXd, sXd, bXd, CU_TENSOR_MAP_SWIZZLE_128B, P256);
    const cuuint64_t dB[4] = {1024, 8, 4, 32}, sB[3] = {2048, 256 * 2048, 8 * 2048};
    const cuuint32_t bB4[4] = {64, 8, 2, 4};
    CUtensorMap tmBre = make_map(enc, d_in[6], 4, dB, sB, bB4, CU_TENSOR_MAP_SWIZZLE_128B, P256);
    CUtensorMap tmBim = make_map(enc, d_in[7], 4, dB, sB, bB4, CU_TENSOR_MAP_SWIZZLE_128B, P256);
    const cuuint64_t dC[5] = {1024, 2, 4, 2, 64}, sC[4] = {2048, 4 * 2048, 2 * 2048, 16 * 2048};
    const cuuint32_t bC[5] = {64, 2, 4, 2, 4};
    CUtensorMap tmCre = make_map(enc, d_in[8], 5, dC, sC, bC, CU_TENSOR_MAP_SWIZZLE_128B, P256);
    CUtensorMap tmCim = make_map(enc, d_in[9], 5, dC, sC, bC, CU_TENSOR_MAP_SWIZZLE_128B, P256);

    const cuuint64_t dU[2] = {8192, 256}, sU[1] = {16384};
    const cuuint32_t bS[2] = {64, UBOX};
    CUtensorMap tmUst = make_map(enc, pU, 2, dU, sU, bS, CU_TENSOR_MAP_SWIZZLE_128B, P0);
    const cuuint64_t dV[3] = {8192, 128, 2}, sV[2] = {32768, 16384};
    const cuuint32_t bV[3] = {32, VBOX, 1};
    CUtensorMap tmVst = make_map(enc, pV, 3, dV, sV, bV, CU_TENSOR_MAP_SWIZZLE_64B, P0);
    const cuuint64_t dA[4] = {1024, 64, 8, 4}, sA[3] = {32 * 2048, 4 * 2048, 2048};
    const cuuint32_t bA[4] = {16, 64, 2, 1};
    CUtensorMap tmXA = make_map(enc, d_in[0], 4, dA, sA, bA, CU_TENSOR_MAP_SWIZZLE_32B, CU_TENSOR_MAP_L2_PROMOTION_L2_128B);
    const cuuint64_t dF[2] = {512 * 1026 / 8, 4}, sF[1] = {512 * 1026};
    const cuuint32_t bF[2] = {WPITCH / 8, 4};
    CUtensorMap tmWr = make_map(enc, d_in[1], 2, dF, sF, bF, CU_TENSOR_MAP_SWIZZLE_NONE, P0, CU_TENSOR_MAP_DATA_TYPE_UINT64);
    CUtensorMap tmWi = make_map(enc, d_in[2], 2, dF, sF, bF, CU_TENSOR_MAP_SWIZZLE_NONE, P0, CU_TENSOR_MAP_DATA_TYPE_UINT64);

    Params p;
    p.wr = (const __nv_bfloat16*)d_in[1];
    p.wi = (const __nv_bfloat16*)d_in[2];
    p.xb = (const __nv_bfloat16*)d_in[3];
    p.lre = (const __nv_bfloat16*)d_in[4];
    p.lim = (const __nv_bfloat16*)d_in[5];
    p.ldt = (const __nv_bfloat16*)d_in[10];
    p.dsk = (const __nv_bfloat16*)d_in[11];
    p.out = (float*)d_out;
    cudaFuncSetAttribute(fused_kernel, cudaFuncAttributeMaxDynamicSharedMemorySize, SMEM_BYTES);
    fused_kernel<<<130, 512, SMEM_BYTES>>>(tmX, tmBre, tmBim, tmCre, tmCim, tmXd, tmUst, tmVst, tmWr, tmWi, tmXA, p);
}
```

```cpp
#include <cuda_runtime.h>
#include <cuda.h>
#include <cuda_bf16.h>
#include <stdint.h>

#define NST 5
#define WPITCH 1056
#define OFF_P (NST * 32768)
#define OFF_F (OFF_P + 32768)
#define OFF_WD (OFF_F + 8192)
#define OFF_WM (OFF_WD + 8 * WPITCH)
#define OFF_BAR (OFF_F + 32768)
#define OFF_LAM (OFF_BAR + 400)
#define OFF_WSP (OFF_LAM + 2048)
#define OFF_PROF (OFF_WSP + 192)
#define SMEM_BYTES OFF_PROF
#define B_FULL 0
#define B_XIN 40
#define B_HL 56
#define B_HR 136
#define B_XD 152
#define B_EP 168
#define B_FG 176
#define B_WSP 184
#define B_WD 192
#define B_WM 200
#define B_VIN 208
#define B_LD 224
#define B_RAW 240
#define B_EMPTY 248
#define B_LAM 288
#define B_STG 296
#define B_WFREE 304
#define B_HOWN 312
#define B_STGU 344
#define B_P3M 352
#define B_UIN 360
#define B_EPOCH 384

#define PACE_U 100
#define PACE_V 100
#define PACE_X 200
#define SKEW 4
#define SPIN_LIMIT (1u << 15)

__device__ __align__(1024) uint8_t g_U[4 << 20];
__device__ __align__(1024) uint8_t g_V[4 << 20];
__device__ __align__(1024) uint8_t g_H[8 << 20];
__device__ __align__(1024) uint4 g_carry[16 * 512];
__device__ __align__(128) unsigned g_cnt[96];
__device__ __align__(128) unsigned g_epoch[132 * 8];

#define STAMP(i) do { } while (0)
#define STAMPR(i) do { } while (0)
#define STAMPW(a, b) do { } while (0)
#define STAMPX(a, b) do { } while (0)
#define STAMP3(i) do { } while (0)

#define TAB_FG 0
#define TAB_G 8192
#define TAB_F1 40960
#define TAB_T 49152
#define TAB_SP 57344
#define TAB_TW1 73728
#define TAB_TW3 75776
#define TAB_PC 83968
__device__ __align__(1024) const uint32_t g_tab[21280] = {
0x80003d80,0x80003d80,0x80003d80,0x80003d80,0x80003d80,0x80003d80,0x80003d80,0x80003d80,0x80003d80,0x80003d80,0x80003d80,0x80003d80,0x80003d80,0x80003d80,0x80003d80,0x80003d80,
0x80003d80,0x80003d80,0x80003d80,0x80003d80,0x80003d80,0x80003d80,0x80003d80,0x80003d80,0x80003d80,0x80003d80,0x80003d80,0x80003d80,0x80003d80,0x80003d80,0x80003d80,0x80003d80,
0x3d353d35,0x3d35bd35,0xbd35bd35,0xbd353d35,0x80003d80,0x3d800000,0x8000bd80,0xbd800000,0x3d353d35,0x3d35bd35,0xbd35bd35,0xbd353d35,0x80003d80,0x3d800000,0x8000bd80,0xbd800000,
0x3d353d35,0x3d35bd35,0xbd35bd35,0xbd353d35,0x80003d80,0x3d800000,0x8000bd80,0xbd800000,0x3d353d35,0x3d35bd35,0xbd35bd35,0xbd353d35,0x80003d80,0x3d800000,0x8000bd80,0xbd800000,
0x3d800000,0x3d6dbcc4,0x3d35bd35,0x3cc4bd6d,0x3d7bbc48,0x3d55bd0e,0x3d0ebd55,0x3c48bd7b,0x80003d80,0x3cc43d6d,0x3d353d35,0x3d6d3cc4,0x3c483d7b,0x3d0e3d55,0x3d553d0e,0x3d7b3c48,
0xbd800000,0xbd6d3cc4,0xbd353d35,0xbcc43d6d,0xbd7b3c48,0xbd553d0e,0xbd0e3d55,0xbc483d7b,0x8000bd80,0xbcc4bd6d,0xbd35bd35,0xbd6dbcc4,0xbc48bd7b,0xbd0ebd55,0xbd55bd0e,0xbd7bbc48,
0x3d0ebd55,0xbd7bbc48,0x3c483d7b,0x3d55bd0e,0x3d800000,0xbcc4bd6d,0xbd353d35,0x3d6d3cc4,0x3d553d0e,0x3c48bd7b,0xbd7b3c48,0x3d0e3d55,0x80003d80,0x3d6dbcc4,0xbd35bd35,0xbcc43d6d,
0xbd0e3d55,0x3d7b3c48,0xbc48bd7b,0xbd553d0e,0xbd800000,0x3cc43d6d,0x3d35bd35,0xbd6dbcc4,0xbd55bd0e,0xbc483d7b,0x3d7bbc48,0xbd0ebd55,0x8000bd80,0xbd6d3cc4,0x3d353d35,0x3cc4bd6d,
0x80003d80,0x3d353d35,0x3d800000,0x3d35bd35,0x3cc43d6d,0x3d6d3cc4,0x3d6dbcc4,0x3cc4bd6d,0x8000bd80,0xbd35bd35,0xbd800000,0xbd353d35,0xbcc4bd6d,0xbd6dbcc4,0xbd6d3cc4,0xbcc43d6d,
0x80003d80,0x3d353d35,0x3d800000,0x3d35bd35,0x3cc43d6d,0x3d6d3cc4,0x3d6dbcc4,0x3cc4bd6d,0x8000bd80,0xbd35bd35,0xbd800000,0xbd353d35,0xbcc4bd6d,0xbd6dbcc4,0xbd6d3cc4,0xbcc43d6d,
0x3d6d3cc4,0xbcc4bd6d,0xbcc43d6d,0x3d6dbcc4,0x80003d80,0x3d35bd35,0xbd800000,0x3d353d35,0xbd6dbcc4,0x3cc43d6d,0x3cc4bd6d,0xbd6d3cc4,0x8000bd80,0xbd353d35,0x3d800000,0xbd35bd35,
0x3d6d3cc4,0xbcc4bd6d,0xbcc43d6d,0x3d6dbcc4,0x80003d80,0x3d35bd35,0xbd800000,0x3d353d35,0xbd6dbcc4,0x3cc43d6d,0x3cc4bd6d,0xbd6d3cc4,0x8000bd80,0xbd353d35,0x3d800000,0xbd35bd35,
0x3d800000,0x3cc4bd6d,0xbd35bd35,0xbd6d3cc4,0x3d55bd0e,0xbc48bd7b,0xbd7bbc48,0xbd0e3d55,0x8000bd80,0xbd6dbcc4,0xbd353d35,0x3cc43d6d,0xbd0ebd55,0xbd7b3c48,0xbc483d7b,0x3d553d0e,
0xbd800000,0xbcc43d6d,0x3d353d35,0x3d6dbcc4,0xbd553d0e,0x3c483d7b,0x3d7b3c48,0x3d0ebd55,0x80003d80,0x3d6d3cc4,0x3d35bd35,0xbcc4bd6d,0x3d0e3d55,0x3d7bbc48,0x3c48bd7b,0xbd55bd0e,
0x3c48bd7b,0xbd0e3d55,0x3d55bd0e,0xbd7b3c48,0x3d800000,0xbd6dbcc4,0x3d353d35,0xbcc4bd6d,0xbd7bbc48,0x3d553d0e,0xbd0ebd55,0x3c483d7b,0x8000bd80,0xbcc43d6d,0x3d35bd35,0xbd6d3cc4,
0xbc483d7b,0x3d0ebd55,0xbd553d0e,0x3d7bbc48,0xbd800000,0x3d6d3cc4,0xbd35bd35,0x3cc43d6d,0x3d7b3c48,0xbd55bd0e,0x3d0e3d55,0xbc48bd7b,0x80003d80,0x3cc4bd6d,0xbd353d35,0x3d6dbcc4,
0x3d800000,0x3d800000,0x3d800000,0x3d800000,0x3d800000,0x3d800000,0x3d800000,0x3d800000,0x3d800000,0x3d800000,0x3d800000,0x3d800000,0x3d800000,0x3d800000,0x3d800000,0x3d800000,
0x3d800000,0x3d800000,0x3d800000,0x3d800000,0x3d800000,0x3d800000,0x3d800000,0x3d800000,0x3d800000,0x3d800000,0x3d800000,0x3d800000,0x3d800000,0x3d800000,0x3d800000,0x3d800000,
0x3d35bd35,0xbd35bd35,0xbd353d35,0x3d353d35,0x3d800000,0xbd80,0xbd800000,0x3d80,0x3d35bd35,0xbd35bd35,0xbd353d35,0x3d353d35,0x3d800000,0xbd80,0xbd800000,0x3d80,
0x3d35bd35,0xbd35bd35,0xbd353d35,0x3d353d35,0x3d800000,0xbd80,0xbd800000,0x3d80,0x3d35bd35,0xbd35bd35,0xbd353d35,0x3d353d35,0x3d800000,0xbd80,0xbd800000,0x3d80,
0xbd80,0xbcc4bd6d,0xbd35bd35,0xbd6dbcc4,0xbc48bd7b,0xbd0ebd55,0xbd55bd0e,0xbd7bbc48,0x3d800000,0x3d6dbcc4,0x3d35bd35,0x3cc4bd6d,0x3d7bbc48,0x3d55bd0e,0x3d0ebd55,0x3c48bd7b,
0x3d80,0x3cc43d6d,0x3d353d35,0x3d6d3cc4,0x3c483d7b,0x3d0e3d55,0x3d553d0e,0x3d7b3c48,0xbd800000,0xbd6d3cc4,0xbd353d35,0xbcc43d6d,0xbd7b3c48,0xbd553d0e,0xbd0e3d55,0xbc483d7b,
0xbd55bd0e,0xbc483d7b,0x3d7bbc48,0xbd0ebd55,0xbd80,0xbd6d3cc4,0x3d353d35,0x3cc4bd6d,0x3d0ebd55,0xbd7bbc48,0x3c483d7b,0x3d55bd0e,0x3d800000,0xbcc4bd6d,0xbd353d35,0x3d6d3cc4,
0x3d553d0e,0x3c48bd7b,0xbd7b3c48,0x3d0e3d55,0x3d80,0x3d6dbcc4,0xbd35bd35,0xbcc43d6d,0xbd0e3d55,0x3d7b3c48,0xbc48bd7b,0xbd553d0e,0xbd800000,0x3cc43d6d,0x3d35bd35,0xbd6dbcc4,
0x3d800000,0x3d35bd35,0xbd80,0xbd35bd35,0x3d6dbcc4,0x3cc4bd6d,0xbcc4bd6d,0xbd6dbcc4,0xbd800000,0xbd353d35,0x3d80,0x3d353d35,0xbd6d3cc4,0xbcc43d6d,0x3cc43d6d,0x3d6d3cc4,
0x3d800000,0x3d35bd35,0xbd80,0xbd35bd35,0x3d6dbcc4,0x3cc4bd6d,0xbcc4bd6d,0xbd6dbcc4,0xbd800000,0xbd353d35,0x3d80,0x3d353d35,0xbd6d3cc4,0xbcc43d6d,0x3cc43d6d,0x3d6d3cc4,
0x3cc4bd6d,0xbd6d3cc4,0x3d6d3cc4,0xbcc4bd6d,0x3d800000,0xbd35bd35,0x3d80,0x3d35bd35,0xbcc43d6d,0x3d6dbcc4,0xbd6dbcc4,0x3cc43d6d,0xbd800000,0x3d353d35,0xbd80,0xbd353d35,
0x3cc4bd6d,0xbd6d3cc4,0x3d6d3cc4,0xbcc4bd6d,0x3d800000,0xbd35bd35,0x3d80,0x3d35bd35,0xbcc43d6d,0x3d6dbcc4,0xbd6dbcc4,0x3cc43d6d,0xbd800000,0x3d353d35,0xbd80,0xbd353d35,
0xbd80,0xbd6dbcc4,0xbd353d35,0x3cc43d6d,0xbd0ebd55,0xbd7b3c48,0xbc483d7b,0x3d553d0e,0xbd800000,0xbcc43d6d,0x3d353d35,0x3d6dbcc4,0xbd553d0e,0x3c483d7b,0x3d7b3c48,0x3d0ebd55,
0x3d80,0x3d6d3cc4,0x3d35bd35,0xbcc4bd6d,0x3d0e3d55,0x3d7bbc48,0x3c48bd7b,0xbd55bd0e,0x3d800000,0x3cc4bd6d,0xbd35bd35,0xbd6d3cc4,0x3d55bd0e,0xbc48bd7b,0xbd7bbc48,0xbd0e3d55,
0xbd7bbc48,0x3d553d0e,0xbd0ebd55,0x3c483d7b,0xbd80,0xbcc43d6d,0x3d35bd35,0xbd6d3cc4,0xbc483d7b,0x3d0ebd55,0xbd553d0e,0x3d7bbc48,0xbd800000,0x3d6d3cc4,0xbd35bd35,0x3cc43d6d,
0x3d7b3c48,0xbd55bd0e,0x3d0e3d55,0xbc48bd7b,0x3d80,0x3cc4bd6d,0xbd353d35,0x3d6dbcc4,0x3c48bd7b,0xbd0e3d55,0x3d55bd0e,0xbd7b3c48,0x3d800000,0xbd6dbcc4,0x3d353d35,0xbcc4bd6d,
0x80003d80,0x8000bd80,0x80003d80,0x8000bd80,0x3d800000,0xbd800000,0x3d800000,0xbd800000,0x80003d80,0x8000bd80,0x80003d80,0x8000bd80,0x3d800000,0xbd800000,0x3d800000,0xbd800000,
0x80003d80,0x8000bd80,0x80003d80,0x8000bd80,0x3d800000,0xbd800000,0x3d800000,0xbd800000,0x80003d80,0x8000bd80,0x80003d80,0x8000bd80,0x3d800000,0xbd800000,0x3d800000,0xbd800000,
0x3d35bd35,0x3d353d35,0xbd353d35,0xbd35bd35,0x80003d80,0xbd800000,0x8000bd80,0x3d800000,0x3d35bd35,0x3d353d35,0xbd353d35,0xbd35bd35,0x80003d80,0xbd800000,0x8000bd80,0x3d800000,
0x3d35bd35,0x3d353d35,0xbd353d35,0xbd35bd35,0x80003d80,0xbd800000,0x8000bd80,0x3d800000,0x3d35bd35,0x3d353d35,0xbd353d35,0xbd35bd35,0x80003d80,0xbd800000,0x8000bd80,0x3d800000,
0x3d800000,0xbd6d3cc4,0x3d35bd35,0xbcc43d6d,0xbc48bd7b,0x3d0e3d55,0xbd55bd0e,0x3d7b3c48,0x80003d80,0xbcc4bd6d,0x3d353d35,0xbd6dbcc4,0x3d7bbc48,0xbd553d0e,0x3d0ebd55,0xbc483d7b,
0xbd800000,0x3d6dbcc4,0xbd353d35,0x3cc4bd6d,0x3c483d7b,0xbd0ebd55,0x3d553d0e,0xbd7bbc48,0x8000bd80,0x3cc43d6d,0xbd35bd35,0x3d6d3cc4,0xbd7b3c48,0x3d55bd0e,0xbd0e3d55,0x3c48bd7b,
0xbd55bd0e,0x3c48bd7b,0x3d7bbc48,0x3d0e3d55,0x3d800000,0x3cc43d6d,0xbd353d35,0xbd6dbcc4,0x3d0ebd55,0x3d7b3c48,0x3c483d7b,0xbd553d0e,0x80003d80,0xbd6d3cc4,0xbd35bd35,0x3cc4bd6d,
0x3d553d0e,0xbc483d7b,0xbd7b3c48,0xbd0ebd55,0xbd800000,0xbcc4bd6d,0x3d35bd35,0x3d6d3cc4,0xbd0e3d55,0xbd7bbc48,0xbc48bd7b,0x3d55bd0e,0x8000bd80,0x3d6dbcc4,0x3d353d35,0xbcc43d6d,
0x80003d80,0xbd35bd35,0x3d800000,0xbd353d35,0x3d6dbcc4,0xbcc43d6d,0xbcc4bd6d,0x3d6d3cc4,0x8000bd80,0x3d353d35,0xbd800000,0x3d35bd35,0xbd6d3cc4,0x3cc4bd6d,0x3cc43d6d,0xbd6dbcc4,
0x80003d80,0xbd35bd35,0x3d800000,0xbd353d35,0x3d6dbcc4,0xbcc43d6d,0xbcc4bd6d,0x3d6d3cc4,0x8000bd80,0x3d353d35,0xbd800000,0x3d35bd35,0xbd6d3cc4,0x3cc4bd6d,0x3cc43d6d,0xbd6dbcc4,
0x3cc4bd6d,0x3d6dbcc4,0x3d6d3cc4,0x3cc43d6d,0x80003d80,0xbd353d35,0xbd800000,0xbd35bd35,0xbcc43d6d,0xbd6d3cc4,0xbd6dbcc4,0xbcc4bd6d,0x8000bd80,0x3d35bd35,0x3d800000,0x3d353d35,
0x3cc4bd6d,0x3d6dbcc4,0x3d6d3cc4,0x3cc43d6d,0x80003d80,0xbd353d35,0xbd800000,0xbd35bd35,0xbcc43d6d,0xbd6d3cc4,0xbd6dbcc4,0xbcc4bd6d,0x8000bd80,0x3d35bd35,0x3d800000,0x3d353d35,
0x3d800000,0xbcc43d6d,0xbd35bd35,0x3d6dbcc4,0xbd0ebd55,0x3d7bbc48,0xbc483d7b,0xbd55bd0e,0x8000bd80,0x3d6d3cc4,0xbd353d35,0xbcc4bd6d,0xbd553d0e,0xbc48bd7b,0x3d7b3c48,0xbd0e3d55,
0xbd800000,0x3cc4bd6d,0x3d353d35,0xbd6d3cc4,0x3d0e3d55,0xbd7b3c48,0x3c48bd7b,0x3d553d0e,0x80003d80,0xbd6dbcc4,0x3d35bd35,0x3cc43d6d,0x3d55bd0e,0x3c483d7b,0xbd7bbc48,0x3d0ebd55,
0xbd7bbc48,0xbd55bd0e,0xbd0ebd55,0xbc48bd7b,0x3d800000,0x3d6d3cc4,0x3d353d35,0x3cc43d6d,0xbc483d7b,0xbd0e3d55,0xbd553d0e,0xbd7b3c48,0x8000bd80,0x3cc4bd6d,0x3d35bd35,0x3d6dbcc4,
0x3d7b3c48,0x3d553d0e,0x3d0e3d55,0x3c483d7b,0xbd800000,0xbd6dbcc4,0xbd35bd35,0xbcc4bd6d,0x3c48bd7b,0x3d0ebd55,0x3d55bd0e,0x3d7bbc48,0x80003d80,0xbcc43d6d,0xbd353d35,0xbd6d3cc4,
0x3d800000,0xbd800000,0x3d800000,0xbd800000,0xbd80,0x3d80,0xbd80,0x3d80,0x3d800000,0xbd800000,0x3d800000,0xbd800000,0xbd80,0x3d80,0xbd80,0x3d80,
0x3d800000,0xbd800000,0x3d800000,0xbd800000,0xbd80,0x3d80,0xbd80,0x3d80,0x3d800000,0xbd800000,0x3d800000,0xbd800000,0xbd80,0x3d80,0xbd80,0x3d80,
0xbd35bd35,0x3d35bd35,0x3d353d35,0xbd353d35,0x3d800000,0x3d80,0xbd800000,0xbd80,0xbd35bd35,0x3d35bd35,0x3d353d35,0xbd353d35,0x3d800000,0x3d80,0xbd800000,0xbd80,
0xbd35bd35,0x3d35bd35,0x3d353d35,0xbd353d35,0x3d800000,0x3d80,0xbd800000,0xbd80,0xbd35bd35,0x3d35bd35,0x3d353d35,0xbd353d35,0x3d800000,0x3d80,0xbd800000,0xbd80,
0xbd80,0x3cc43d6d,0xbd35bd35,0x3d6d3cc4,0xbd7b3c48,0x3d55bd0e,0xbd0e3d55,0x3c48bd7b,0x3d800000,0xbd6d3cc4,0x3d35bd35,0xbcc43d6d,0xbc48bd7b,0x3d0e3d55,0xbd55bd0e,0x3d7b3c48,
0x3d80,0xbcc4bd6d,0x3d353d35,0xbd6dbcc4,0x3d7bbc48,0xbd553d0e,0x3d0ebd55,0xbc483d7b,0xbd800000,0x3d6dbcc4,0xbd353d35,0x3cc4bd6d,0x3c483d7b,0xbd0ebd55,0x3d553d0e,0xbd7bbc48,
0xbd0e3d55,0xbd7bbc48,0xbc48bd7b,0x3d55bd0e,0xbd80,0x3d6dbcc4,0x3d353d35,0xbcc43d6d,0xbd55bd0e,0x3c48bd7b,0x3d7bbc48,0x3d0e3d55,0x3d800000,0x3cc43d6d,0xbd353d35,0xbd6dbcc4,
0x3d0ebd55,0x3d7b3c48,0x3c483d7b,0xbd553d0e,0x3d80,0xbd6d3cc4,0xbd35bd35,0x3cc4bd6d,0x3d553d0e,0xbc483d7b,0xbd7b3c48,0xbd0ebd55,0xbd800000,0xbcc4bd6d,0x3d35bd35,0x3d6d3cc4,
0x3d800000,0xbd353d35,0xbd80,0x3d353d35,0xbcc4bd6d,0x3d6d3cc4,0xbd6d3cc4,0x3cc4bd6d,0xbd800000,0x3d35bd35,0x3d80,0xbd35bd35,0x3cc43d6d,0xbd6dbcc4,0x3d6dbcc4,0xbcc43d6d,
0x3d800000,0xbd353d35,0xbd80,0x3d353d35,0xbcc4bd6d,0x3d6d3cc4,0xbd6d3cc4,0x3cc4bd6d,0xbd800000,0x3d35bd35,0x3d80,0xbd35bd35,0x3cc43d6d,0xbd6dbcc4,0x3d6dbcc4,0xbcc43d6d,
0xbd6dbcc4,0xbcc4bd6d,0x3cc4bd6d,0x3d6dbcc4,0x3d800000,0x3d353d35,0x3d80,0xbd353d35,0x3d6d3cc4,0x3cc43d6d,0xbcc43d6d,0xbd6d3cc4,0xbd800000,0xbd35bd35,0xbd80,0x3d35bd35,
0xbd6dbcc4,0xbcc4bd6d,0x3cc4bd6d,0x3d6dbcc4,0x3d800000,0x3d353d35,0x3d80,0xbd353d35,0x3d6d3cc4,0x3cc43d6d,0xbcc43d6d,0xbd6d3cc4,0xbd800000,0xbd35bd35,0xbd80,0x3d35bd35,
0xbd80,0x3d6d3cc4,0xbd353d35,0xbcc4bd6d,0xbd553d0e,0xbc48bd7b,0x3d7b3c48,0xbd0e3d55,0xbd800000,0x3cc4bd6d,0x3d353d35,0xbd6d3cc4,0x3d0e3d55,0xbd7b3c48,0x3c48bd7b,0x3d553d0e,
0x3d80,0xbd6dbcc4,0x3d35bd35,0x3cc43d6d,0x3d55bd0e,0x3c483d7b,0xbd7bbc48,0x3d0ebd55,0x3d800000,0xbcc43d6d,0xbd35bd35,0x3d6dbcc4,0xbd0ebd55,0x3d7bbc48,0xbc483d7b,0xbd55bd0e,
0xbc483d7b,0xbd0e3d55,0xbd553d0e,0xbd7b3c48,0xbd80,0x3cc4bd6d,0x3d35bd35,0x3d6dbcc4,0x3d7b3c48,0x3d553d0e,0x3d0e3d55,0x3c483d7b,0xbd800000,0xbd6dbcc4,0xbd35bd35,0xbcc4bd6d,
0x3c48bd7b,0x3d0ebd55,0x3d55bd0e,0x3d7bbc48,0x3d80,0xbcc43d6d,0xbd353d35,0xbd6d3cc4,0xbd7bbc48,0xbd55bd0e,0xbd0ebd55,0xbc48bd7b,0x3d800000,0x3d6d3cc4,0x3d353d35,0x3cc43d6d,
0x80003d80,0x80003d80,0x80003d80,0x80003d80,0x8000bd80,0x8000bd80,0x8000bd80,0x8000bd80,0x80003d80,0x80003d80,0x80003d80,0x80003d80,0x8000bd80,0x8000bd80,0x8000bd80,0x8000bd80,
0x80003d80,0x80003d80,0x80003d80,0x80003d80,0x8000bd80,0x8000bd80,0x8000bd80,0x8000bd80,0x80003d80,0x80003d80,0x80003d80,0x80003d80,0x8000bd80,0x8000bd80,0x8000bd80,0x8000bd80,
0xbd35bd35,0xbd353d35,0x3d353d35,0x3d35bd35,0x80003d80,0x3d800000,0x8000bd80,0xbd800000,0xbd35bd35,0xbd353d35,0x3d353d35,0x3d35bd35,0x80003d80,0x3d800000,0x8000bd80,0xbd800000,
0xbd35bd35,0xbd353d35,0x3d353d35,0x3d35bd35,0x80003d80,0x3d800000,0x8000bd80,0xbd800000,0xbd35bd35,0xbd353d35,0x3d353d35,0x3d35bd35,0x80003d80,0x3d800000,0x8000bd80,0xbd800000,
0x3d800000,0x3d6dbcc4,0x3d35bd35,0x3cc4bd6d,0xbd7b3c48,0xbd553d0e,0xbd0e3d55,0xbc483d7b,0x80003d80,0x3cc43d6d,0x3d353d35,0x3d6d3cc4,0xbc48bd7b,0xbd0ebd55,0xbd55bd0e,0xbd7bbc48,
0xbd800000,0xbd6d3cc4,0xbd353d35,0xbcc43d6d,0x3d7bbc48,0x3d55bd0e,0x3d0ebd55,0x3c48bd7b,0x8000bd80,0xbcc4bd6d,0xbd35bd35,0xbd6dbcc4,0x3c483d7b,0x3d0e3d55,0x3d553d0e,0x3d7b3c48,
0xbd0e3d55,0x3d7b3c48,0xbc48bd7b,0xbd553d0e,0x3d800000,0xbcc4bd6d,0xbd353d35,0x3d6d3cc4,0xbd55bd0e,0xbc483d7b,0x3d7bbc48,0xbd0ebd55,0x80003d80,0x3d6dbcc4,0xbd35bd35,0xbcc43d6d,
0x3d0ebd55,0xbd7bbc48,0x3c483d7b,0x3d55bd0e,0xbd800000,0x3cc43d6d,0x3d35bd35,0xbd6dbcc4,0x3d553d0e,0x3c48bd7b,0xbd7b3c48,0x3d0e3d55,0x8000bd80,0xbd6d3cc4,0x3d353d35,0x3cc4bd6d,
0x80003d80,0x3d353d35,0x3d800000,0x3d35bd35,0xbcc4bd6d,0xbd6dbcc4,0xbd6d3cc4,0xbcc43d6d,0x8000bd80,0xbd35bd35,0xbd800000,0xbd353d35,0x3cc43d6d,0x3d6d3cc4,0x3d6dbcc4,0x3cc4bd6d,
0x80003d80,0x3d353d35,0x3d800000,0x3d35bd35,0xbcc4bd6d,0xbd6dbcc4,0xbd6d3cc4,0xbcc43d6d,0x8000bd80,0xbd35bd35,0xbd800000,0xbd353d35,0x3cc43d6d,0x3d6d3cc4,0x3d6dbcc4,0x3cc4bd6d,
0xbd6dbcc4,0x3cc43d6d,0x3cc4bd6d,0xbd6d3cc4,0x80003d80,0x3d35bd35,0xbd800000,0x3d353d35,0x3d6d3cc4,0xbcc4bd6d,0xbcc43d6d,0x3d6dbcc4,0x8000bd80,0xbd353d35,0x3d800000,0xbd35bd35,
0xbd6dbcc4,0x3cc43d6d,0x3cc4bd6d,0xbd6d3cc4,0x80003d80,0x3d35bd35,0xbd800000,0x3d353d35,0x3d6d3cc4,0xbcc4bd6d,0xbcc43d6d,0x3d6dbcc4,0x8000bd80,0xbd353d35,0x3d800000,0xbd35bd35,
0x3d800000,0x3cc4bd6d,0xbd35bd35,0xbd6d3cc4,0xbd553d0e,0x3c483d7b,0x3d7b3c48,0x3d0ebd55,0x8000bd80,0xbd6dbcc4,0xbd353d35,0x3cc43d6d,0x3d0e3d55,0x3d7bbc48,0x3c48bd7b,0xbd55bd0e,
0xbd800000,0xbcc43d6d,0x3d353d35,0x3d6dbcc4,0x3d55bd0e,0xbc48bd7b,0xbd7bbc48,0xbd0e3d55,0x80003d80,0x3d6d3cc4,0x3d35bd35,0xbcc4bd6d,0xbd0ebd55,0xbd7b3c48,0xbc483d7b,0x3d553d0e,
0xbc483d7b,0x3d0ebd55,0xbd553d0e,0x3d7bbc48,0x3d800000,0xbd6dbcc4,0x3d353d35,0xbcc4bd6d,0x3d7b3c48,0xbd55bd0e,0x3d0e3d55,0xbc48bd7b,0x8000bd80,0xbcc43d6d,0x3d35bd35,0xbd6d3cc4,
0x3c48bd7b,0xbd0e3d55,0x3d55bd0e,0xbd7b3c48,0xbd800000,0x3d6d3cc4,0xbd35bd35,0x3cc43d6d,0xbd7bbc48,0x3d553d0e,0xbd0ebd55,0x3c483d7b,0x80003d80,0x3cc4bd6d,0xbd353d35,0x3d6dbcc4,
0x3d800000,0x3d800000,0x3d800000,0x3d800000,0xbd800000,0xbd800000,0xbd800000,0xbd800000,0x3d800000,0x3d800000,0x3d800000,0x3d800000,0xbd800000,0xbd800000,0xbd800000,0xbd800000,
0x3d800000,0x3d800000,0x3d800000,0x3d800000,0xbd800000,0xbd800000,0xbd800000,0xbd800000,0x3d800000,0x3d800000,0x3d800000,0x3d800000,0xbd800000,0xbd800000,0xbd800000,0xbd800000,
0xbd353d35,0x3d353d35,0x3d35bd35,0xbd35bd35,0x3d800000,0xbd80,0xbd800000,0x3d80,0xbd353d35,0x3d353d35,0x3d35bd35,0xbd35bd35,0x3d800000,0xbd80,0xbd800000,0x3d80,
0xbd353d35,0x3d353d35,0x3d35bd35,0xbd35bd35,0x3d800000,0xbd80,0xbd800000,0x3d80,0xbd353d35,0x3d353d35,0x3d35bd35,0xbd35bd35,0x3d800000,0xbd80,0xbd800000,0x3d80,
0xbd80,0xbcc4bd6d,0xbd35bd35,0xbd6dbcc4,0x3c483d7b,0x3d0e3d55,0x3d553d0e,0x3d7b3c48,0x3d800000,0x3d6dbcc4,0x3d35bd35,0x3cc4bd6d,0xbd7b3c48,0xbd553d0e,0xbd0e3d55,0xbc483d7b,
0x3d80,0x3cc43d6d,0x3d353d35,0x3d6d3cc4,0xbc48bd7b,0xbd0ebd55,0xbd55bd0e,0xbd7bbc48,0xbd800000,0xbd6d3cc4,0xbd353d35,0xbcc43d6d,0x3d7bbc48,0x3d55bd0e,0x3d0ebd55,0x3c48bd7b,
0x3d553d0e,0x3c48bd7b,0xbd7b3c48,0x3d0e3d55,0xbd80,0xbd6d3cc4,0x3d353d35,0x3cc4bd6d,0xbd0e3d55,0x3d7b3c48,0xbc48bd7b,0xbd553d0e,0x3d800000,0xbcc4bd6d,0xbd353d35,0x3d6d3cc4,
0xbd55bd0e,0xbc483d7b,0x3d7bbc48,0xbd0ebd55,0x3d80,0x3d6dbcc4,0xbd35bd35,0xbcc43d6d,0x3d0ebd55,0xbd7bbc48,0x3c483d7b,0x3d55bd0e,0xbd800000,0x3cc43d6d,0x3d35bd35,0xbd6dbcc4,
0x3d800000,0x3d35bd35,0xbd80,0xbd35bd35,0xbd6d3cc4,0xbcc43d6d,0x3cc43d6d,0x3d6d3cc4,0xbd800000,0xbd353d35,0x3d80,0x3d353d35,0x3d6dbcc4,0x3cc4bd6d,0xbcc4bd6d,0xbd6dbcc4,
0x3d800000,0x3d35bd35,0xbd80,0xbd35bd35,0xbd6d3cc4,0xbcc43d6d,0x3cc43d6d,0x3d6d3cc4,0xbd800000,0xbd353d35,0x3d80,0x3d353d35,0x3d6dbcc4,0x3cc4bd6d,0xbcc4bd6d,0xbd6dbcc4,
0xbcc43d6d,0x3d6dbcc4,0xbd6dbcc4,0x3cc43d6d,0x3d800000,0xbd35bd35,0x3d80,0x3d35bd35,0x3cc4bd6d,0xbd6d3cc4,0x3d6d3cc4,0xbcc4bd6d,0xbd800000,0x3d353d35,0xbd80,0xbd353d35,
0xbcc43d6d,0x3d6dbcc4,0xbd6dbcc4,0x3cc43d6d,0x3d800000,0xbd35bd35,0x3d80,0x3d35bd35,0x3cc4bd6d,0xbd6d3cc4,0x3d6d3cc4,0xbcc4bd6d,0xbd800000,0x3d353d35,0xbd80,0xbd353d35,
0xbd80,0xbd6dbcc4,0xbd353d35,0x3cc43d6d,0x3d0e3d55,0x3d7bbc48,0x3c48bd7b,0xbd55bd0e,0xbd800000,0xbcc43d6d,0x3d353d35,0x3d6dbcc4,0x3d55bd0e,0xbc48bd7b,0xbd7bbc48,0xbd0e3d55,
0x3d80,0x3d6d3cc4,0x3d35bd35,0xbcc4bd6d,0xbd0ebd55,0xbd7b3c48,0xbc483d7b,0x3d553d0e,0x3d800000,0x3cc4bd6d,0xbd35bd35,0xbd6d3cc4,0xbd553d0e,0x3c483d7b,0x3d7b3c48,0x3d0ebd55,
0x3d7b3c48,0xbd55bd0e,0x3d0e3d55,0xbc48bd7b,0xbd80,0xbcc43d6d,0x3d35bd35,0xbd6d3cc4,0x3c48bd7b,0xbd0e3d55,0x3d55bd0e,0xbd7b3c48,0xbd800000,0x3d6d3cc4,0xbd35bd35,0x3cc43d6d,
0xbd7bbc48,0x3d553d0e,0xbd0ebd55,0x3c483d7b,0x3d80,0x3cc4bd6d,0xbd353d35,0x3d6dbcc4,0xbc483d7b,0x3d0ebd55,0xbd553d0e,0x3d7bbc48,0x3d800000,0xbd6dbcc4,0x3d353d35,0xbcc4bd6d,
0x80003d80,0x8000bd80,0x80003d80,0x8000bd80,0xbd800000,0x3d800000,0xbd800000,0x3d800000,0x80003d80,0x8000bd80,0x80003d80,0x8000bd80,0xbd800000,0x3d800000,0xbd800000,0x3d800000,
0x80003d80,0x8000bd80,0x80003d80,0x8000bd80,0xbd800000,0x3d800000,0xbd800000,0x3d800000,0x80003d80,0x8000bd80,0x80003d80,0x8000bd80,0xbd800000,0x3d800000,0xbd800000,0x3d800000,
0xbd353d35,0xbd35bd35,0x3d35bd35,0x3d353d35,0x80003d80,0xbd800000,0x8000bd80,0x3d800000,0xbd353d35,0xbd35bd35,0x3d35bd35,0x3d353d35,0x80003d80,0xbd800000,0x8000bd80,0x3d800000,
0xbd353d35,0xbd35bd35,0x3d35bd35,0x3d353d35,0x80003d80,0xbd800000,0x8000bd80,0x3d800000,0xbd353d35,0xbd35bd35,0x3d35bd35,0x3d353d35,0x80003d80,0xbd800000,0x8000bd80,0x3d800000,
0x3d800000,0xbd6d3cc4,0x3d35bd35,0xbcc43d6d,0x3c483d7b,0xbd0ebd55,0x3d553d0e,0xbd7bbc48,0x80003d80,0xbcc4bd6d,0x3d353d35,0xbd6dbcc4,0xbd7b3c48,0x3d55bd0e,0xbd0e3d55,0x3c48bd7b,
0xbd800000,0x3d6dbcc4,0xbd353d35,0x3cc4bd6d,0xbc48bd7b,0x3d0e3d55,0xbd55bd0e,0x3d7b3c48,0x8000bd80,0x3cc43d6d,0xbd35bd35,0x3d6d3cc4,0x3d7bbc48,0xbd553d0e,0x3d0ebd55,0xbc483d7b,
0x3d553d0e,0xbc483d7b,0xbd7b3c48,0xbd0ebd55,0x3d800000,0x3cc43d6d,0xbd353d35,0xbd6dbcc4,0xbd0e3d55,0xbd7bbc48,0xbc48bd7b,0x3d55bd0e,0x80003d80,0xbd6d3cc4,0xbd35bd35,0x3cc4bd6d,
0xbd55bd0e,0x3c48bd7b,0x3d7bbc48,0x3d0e3d55,0xbd800000,0xbcc4bd6d,0x3d35bd35,0x3d6d3cc4,0x3d0ebd55,0x3d7b3c48,0x3c483d7b,0xbd553d0e,0x8000bd80,0x3d6dbcc4,0x3d353d35,0xbcc43d6d,
0x80003d80,0xbd35bd35,0x3d800000,0xbd353d35,0xbd6d3cc4,0x3cc4bd6d,0x3cc43d6d,0xbd6dbcc4,0x8000bd80,0x3d353d35,0xbd800000,0x3d35bd35,0x3d6dbcc4,0xbcc43d6d,0xbcc4bd6d,0x3d6d3cc4,
0x80003d80,0xbd35bd35,0x3d800000,0xbd353d35,0xbd6d3cc4,0x3cc4bd6d,0x3cc43d6d,0xbd6dbcc4,0x8000bd80,0x3d353d35,0xbd800000,0x3d35bd35,0x3d6dbcc4,0xbcc43d6d,0xbcc4bd6d,0x3d6d3cc4,
0xbcc43d6d,0xbd6d3cc4,0xbd6dbcc4,0xbcc4bd6d,0x80003d80,0xbd353d35,0xbd800000,0xbd35bd35,0x3cc4bd6d,0x3d6dbcc4,0x3d6d3cc4,0x3cc43d6d,0x8000bd80,0x3d35bd35,0x3d800000,0x3d353d35,
0xbcc43d6d,0xbd6d3cc4,0xbd6dbcc4,0xbcc4bd6d,0x80003d80,0xbd353d35,0xbd800000,0xbd35bd35,0x3cc4bd6d,0x3d6dbcc4,0x3d6d3cc4,0x3cc43d6d,0x8000bd80,0x3d35bd35,0x3d800000,0x3d353d35,
0x3d800000,0xbcc43d6d,0xbd35bd35,0x3d6dbcc4,0x3d0e3d55,0xbd7b3c48,0x3c48bd7b,0x3d553d0e,0x8000bd80,0x3d6d3cc4,0xbd353d35,0xbcc4bd6d,0x3d55bd0e,0x3c483d7b,0xbd7bbc48,0x3d0ebd55,
0xbd800000,0x3cc4bd6d,0x3d353d35,0xbd6d3cc4,0xbd0ebd55,0x3d7bbc48,0xbc483d7b,0xbd55bd0e,0x80003d80,0xbd6dbcc4,0x3d35bd35,0x3cc43d6d,0xbd553d0e,0xbc48bd7b,0x3d7b3c48,0xbd0e3d55,
0x3d7b3c48,0x3d553d0e,0x3d0e3d55,0x3c483d7b,0x3d800000,0x3d6d3cc4,0x3d353d35,0x3cc43d6d,0x3c48bd7b,0x3d0ebd55,0x3d55bd0e,0x3d7bbc48,0x8000bd80,0x3cc4bd6d,0x3d35bd35,0x3d6dbcc4,
0xbd7bbc48,0xbd55bd0e,0xbd0ebd55,0xbc48bd7b,0xbd800000,0xbd6dbcc4,0xbd35bd35,0xbcc4bd6d,0xbc483d7b,0xbd0e3d55,0xbd553d0e,0xbd7b3c48,0x80003d80,0xbcc43d6d,0xbd353d35,0xbd6d3cc4,
0x3d800000,0xbd800000,0x3d800000,0xbd800000,0x3d80,0xbd80,0x3d80,0xbd80,0x3d800000,0xbd800000,0x3d800000,0xbd800000,0x3d80,0xbd80,0x3d80,0xbd80,
0x3d800000,0xbd800000,0x3d800000,0xbd800000,0x3d80,0xbd80,0x3d80,0xbd80,0x3d800000,0xbd800000,0x3d800000,0xbd800000,0x3d80,0xbd80,0x3d80,0xbd80,
0x3d353d35,0xbd353d35,0xbd35bd35,0x3d35bd35,0x3d800000,0x3d80,0xbd800000,0xbd80,0x3d353d35,0xbd353d35,0xbd35bd35,0x3d35bd35,0x3d800000,0x3d80,0xbd800000,0xbd80,
0x3d353d35,0xbd353d35,0xbd35bd35,0x3d35bd35,0x3d800000,0x3d80,0xbd800000,0xbd80,0x3d353d35,0xbd353d35,0xbd35bd35,0x3d35bd35,0x3d800000,0x3d80,0xbd800000,0xbd80,
0xbd80,0x3cc43d6d,0xbd35bd35,0x3d6d3cc4,0x3d7bbc48,0xbd553d0e,0x3d0ebd55,0xbc483d7b,0x3d800000,0xbd6d3cc4,0x3d35bd35,0xbcc43d6d,0x3c483d7b,0xbd0ebd55,0x3d553d0e,0xbd7bbc48,
0x3d80,0xbcc4bd6d,0x3d353d35,0xbd6dbcc4,0xbd7b3c48,0x3d55bd0e,0xbd0e3d55,0x3c48bd7b,0xbd800000,0x3d6dbcc4,0xbd353d35,0x3cc4bd6d,0xbc48bd7b,0x3d0e3d55,0xbd55bd0e,0x3d7b3c48,
0x3d0ebd55,0x3d7b3c48,0x3c483d7b,0xbd553d0e,0xbd80,0x3d6dbcc4,0x3d353d35,0xbcc43d6d,0x3d553d0e,0xbc483d7b,0xbd7b3c48,0xbd0ebd55,0x3d800000,0x3cc43d6d,0xbd353d35,0xbd6dbcc4,
0xbd0e3d55,0xbd7bbc48,0xbc48bd7b,0x3d55bd0e,0x3d80,0xbd6d3cc4,0xbd35bd35,0x3cc4bd6d,0xbd55bd0e,0x3c48bd7b,0x3d7bbc48,0x3d0e3d55,0xbd800000,0xbcc4bd6d,0x3d35bd35,0x3d6d3cc4,
0x3d800000,0xbd353d35,0xbd80,0x3d353d35,0x3cc43d6d,0xbd6dbcc4,0x3d6dbcc4,0xbcc43d6d,0xbd800000,0x3d35bd35,0x3d80,0xbd35bd35,0xbcc4bd6d,0x3d6d3cc4,0xbd6d3cc4,0x3cc4bd6d,
0x3d800000,0xbd353d35,0xbd80,0x3d353d35,0x3cc43d6d,0xbd6dbcc4,0x3d6dbcc4,0xbcc43d6d,0xbd800000,0x3d35bd35,0x3d80,0xbd35bd35,0xbcc4bd6d,0x3d6d3cc4,0xbd6d3cc4,0x3cc4bd6d,
0x3d6d3cc4,0x3cc43d6d,0xbcc43d6d,0xbd6d3cc4,0x3d800000,0x3d353d35,0x3d80,0xbd353d35,0xbd6dbcc4,0xbcc4bd6d,0x3cc4bd6d,0x3d6dbcc4,0xbd800000,0xbd35bd35,0xbd80,0x3d35bd35,
0x3d6d3cc4,0x3cc43d6d,0xbcc43d6d,0xbd6d3cc4,0x3d800000,0x3d353d35,0x3d80,0xbd353d35,0xbd6dbcc4,0xbcc4bd6d,0x3cc4bd6d,0x3d6dbcc4,0xbd800000,0xbd35bd35,0xbd80,0x3d35bd35,
0xbd80,0x3d6d3cc4,0xbd353d35,0xbcc4bd6d,0x3d55bd0e,0x3c483d7b,0xbd7bbc48,0x3d0ebd55,0xbd800000,0x3cc4bd6d,0x3d353d35,0xbd6d3cc4,0xbd0ebd55,0x3d7bbc48,0xbc483d7b,0xbd55bd0e,
0x3d80,0xbd6dbcc4,0x3d35bd35,0x3cc43d6d,0xbd553d0e,0xbc48bd7b,0x3d7b3c48,0xbd0e3d55,0x3d800000,0xbcc43d6d,0xbd35bd35,0x3d6dbcc4,0x3d0e3d55,0xbd7b3c48,0x3c48bd7b,0x3d553d0e,
0x3c48bd7b,0x3d0ebd55,0x3d55bd0e,0x3d7bbc48,0xbd80,0x3cc4bd6d,0x3d35bd35,0x3d6dbcc4,0xbd7bbc48,0xbd55bd0e,0xbd0ebd55,0xbc48bd7b,0xbd800000,0xbd6dbcc4,0xbd35bd35,0xbcc4bd6d,
0xbc483d7b,0xbd0e3d55,0xbd553d0e,0xbd7b3c48,0x3d80,0xbcc43d6d,0xbd353d35,0xbd6d3cc4,0x3d7b3c48,0x3d553d0e,0x3d0e3d55,0x3c483d7b,0x3d800000,0x3d6d3cc4,0x3d353d35,0x3cc43d6d,
0x3d80,0x3d80,0x3d80,0x3d80,0x3d80,0x3d80,0x3d80,0x3d80,0x3d80,0x3d80,0x3d80,0x3d80,0x3d80,0x3d80,0x3d80,0x3d80,
0x3d80,0x3d80,0x3d80,0x3d80,0x3d80,0x3d80,0x3d80,0x3d80,0x3d80,0x3d80,0x3d80,0x3d80,0x3d80,0x3d80,0x3d80,0x3d80,
0xbd353d35,0xbd553d0e,0xbd6d3cc4,0xbd7b3c48,0x3d80,0xbc483d7b,0xbcc43d6d,0xbd0e3d55,0xbd35bd35,0xbd0ebd55,0xbcc4bd6d,0xbc48bd7b,0xbd800000,0xbd7bbc48,0xbd6dbcc4,0xbd55bd0e,
0x3d35bd35,0x3d55bd0e,0x3d6dbcc4,0x3d7bbc48,0xbd80,0x3c48bd7b,0x3cc4bd6d,0x3d0ebd55,0x3d353d35,0x3d0e3d55,0x3cc43d6d,0x3c483d7b,0x3d800000,0x3d7b3c48,0x3d6d3cc4,0x3d553d0e,
0xbd80,0x3cc4bd6d,0x3d35bd35,0x3d6dbcc4,0x3d800000,0x3d6d3cc4,0x3d353d35,0x3cc43d6d,0x3d80,0xbcc43d6d,0xbd353d35,0xbd6d3cc4,0xbd800000,0xbd6dbcc4,0xbd35bd35,0xbcc4bd6d,
0xbd80,0x3cc4bd6d,0x3d35bd35,0x3d6dbcc4,0x3d800000,0x3d6d3cc4,0x3d353d35,0x3cc43d6d,0x3d80,0xbcc43d6d,0xbd353d35,0xbd6d3cc4,0xbd800000,0xbd6dbcc4,0xbd35bd35,0xbcc4bd6d,
0xbd353d35,0xbd7b3c48,0xbd6dbcc4,0xbd0ebd55,0x3d800000,0x3d553d0e,0x3cc43d6d,0xbc483d7b,0xbd35bd35,0xbc48bd7b,0x3cc4bd6d,0x3d55bd0e,0x3d80,0xbd0e3d55,0xbd6d3cc4,0xbd7bbc48,
0x3d35bd35,0x3d7bbc48,0x3d6d3cc4,0x3d0e3d55,0xbd800000,0xbd55bd0e,0xbcc4bd6d,0x3c48bd7b,0x3d353d35,0x3c483d7b,0xbcc43d6d,0xbd553d0e,0xbd80,0x3d0ebd55,0x3d6dbcc4,0x3d7b3c48,
0x3d80,0xbd353d35,0xbd800000,0xbd35bd35,0xbd80,0x3d35bd35,0x3d800000,0x3d353d35,0x3d80,0xbd353d35,0xbd800000,0xbd35bd35,0xbd80,0x3d35bd35,0x3d800000,0x3d353d35,
0x3d80,0xbd353d35,0xbd800000,0xbd35bd35,0xbd80,0x3d35bd35,0x3d800000,0x3d353d35,0x3d80,0xbd353d35,0xbd800000,0xbd35bd35,0xbd80,0x3d35bd35,0x3d800000,0x3d353d35,
0xbd353d35,0xbd7bbc48,0xbcc4bd6d,0x3d0ebd55,0xbd80,0x3d55bd0e,0x3d6d3cc4,0x3c483d7b,0xbd35bd35,0x3c48bd7b,0x3d6dbcc4,0x3d553d0e,0x3d800000,0x3d0e3d55,0xbcc43d6d,0xbd7b3c48,
0x3d35bd35,0x3d7b3c48,0x3cc43d6d,0xbd0e3d55,0x3d80,0xbd553d0e,0xbd6dbcc4,0xbc48bd7b,0x3d353d35,0xbc483d7b,0xbd6d3cc4,0xbd55bd0e,0xbd800000,0xbd0ebd55,0x3cc4bd6d,0x3d7bbc48,
0xbd80,0x3d6dbcc4,0x3d353d35,0xbcc43d6d,0xbd800000,0xbcc4bd6d,0x3d35bd35,0x3d6d3cc4,0x3d80,0xbd6d3cc4,0xbd35bd35,0x3cc4bd6d,0x3d800000,0x3cc43d6d,0xbd353d35,0xbd6dbcc4,
0xbd80,0x3d6dbcc4,0x3d353d35,0xbcc43d6d,0xbd800000,0xbcc4bd6d,0x3d35bd35,0x3d6d3cc4,0x3d80,0xbd6d3cc4,0xbd35bd35,0x3cc4bd6d,0x3d800000,0x3cc43d6d,0xbd353d35,0xbd6dbcc4,
0xbd353d35,0xbd55bd0e,0x3cc4bd6d,0x3d7b3c48,0xbd800000,0xbc48bd7b,0x3d6dbcc4,0x3d0e3d55,0xbd35bd35,0x3d0ebd55,0x3d6d3cc4,0xbc483d7b,0xbd80,0x3d7bbc48,0x3cc43d6d,0xbd553d0e,
0x3d35bd35,0x3d553d0e,0xbcc43d6d,0xbd7bbc48,0x3d800000,0x3c483d7b,0xbd6d3cc4,0xbd0ebd55,0x3d353d35,0xbd0e3d55,0xbd6dbcc4,0x3c48bd7b,0x3d80,0xbd7b3c48,0xbcc4bd6d,0x3d55bd0e,
0xbd800000,0xbd800000,0xbd800000,0xbd800000,0xbd800000,0xbd800000,0xbd800000,0xbd800000,0xbd800000,0xbd800000,0xbd800000,0xbd800000,0xbd800000,0xbd800000,0xbd800000,0xbd800000,
0xbd800000,0xbd800000,0xbd800000,0xbd800000,0xbd800000,0xbd800000,0xbd800000,0xbd800000,0xbd800000,0xbd800000,0xbd800000,0xbd800000,0xbd800000,0xbd800000,0xbd800000,0xbd800000,
0xbd35bd35,0xbd0ebd55,0xbcc4bd6d,0xbc48bd7b,0xbd800000,0xbd7bbc48,0xbd6dbcc4,0xbd55bd0e,0x3d35bd35,0x3d55bd0e,0x3d6dbcc4,0x3d7bbc48,0x8000bd80,0x3c48bd7b,0x3cc4bd6d,0x3d0ebd55,
0x3d353d35,0x3d0e3d55,0x3cc43d6d,0x3c483d7b,0x3d800000,0x3d7b3c48,0x3d6d3cc4,0x3d553d0e,0xbd353d35,0xbd553d0e,0xbd6d3cc4,0xbd7b3c48,0x80003d80,0xbc483d7b,0xbcc43d6d,0xbd0e3d55,
0x3d800000,0x3d6d3cc4,0x3d353d35,0x3cc43d6d,0x80003d80,0xbcc43d6d,0xbd353d35,0xbd6d3cc4,0xbd800000,0xbd6dbcc4,0xbd35bd35,0xbcc4bd6d,0x8000bd80,0x3cc4bd6d,0x3d35bd35,0x3d6dbcc4,
0x3d800000,0x3d6d3cc4,0x3d353d35,0x3cc43d6d,0x80003d80,0xbcc43d6d,0xbd353d35,0xbd6d3cc4,0xbd800000,0xbd6dbcc4,0xbd35bd35,0xbcc4bd6d,0x8000bd80,0x3cc4bd6d,0x3d35bd35,0x3d6dbcc4,
0xbd35bd35,0xbc48bd7b,0x3cc4bd6d,0x3d55bd0e,0x80003d80,0xbd0e3d55,0xbd6d3cc4,0xbd7bbc48,0x3d35bd35,0x3d7bbc48,0x3d6d3cc4,0x3d0e3d55,0xbd800000,0xbd55bd0e,0xbcc4bd6d,0x3c48bd7b,
0x3d353d35,0x3c483d7b,0xbcc43d6d,0xbd553d0e,0x8000bd80,0x3d0ebd55,0x3d6dbcc4,0x3d7b3c48,0xbd353d35,0xbd7b3c48,0xbd6dbcc4,0xbd0ebd55,0x3d800000,0x3d553d0e,0x3cc43d6d,0xbc483d7b,
0xbd800000,0xbd35bd35,0x8000bd80,0x3d35bd35,0x3d800000,0x3d353d35,0x80003d80,0xbd353d35,0xbd800000,0xbd35bd35,0x8000bd80,0x3d35bd35,0x3d800000,0x3d353d35,0x80003d80,0xbd353d35,
0xbd800000,0xbd35bd35,0x8000bd80,0x3d35bd35,0x3d800000,0x3d353d35,0x80003d80,0xbd353d35,0xbd800000,0xbd35bd35,0x8000bd80,0x3d35bd35,0x3d800000,0x3d353d35,0x80003d80,0xbd353d35,
0xbd35bd35,0x3c48bd7b,0x3d6dbcc4,0x3d553d0e,0x3d800000,0x3d0e3d55,0xbcc43d6d,0xbd7b3c48,0x3d35bd35,0x3d7b3c48,0x3cc43d6d,0xbd0e3d55,0x80003d80,0xbd553d0e,0xbd6dbcc4,0xbc48bd7b,
0x3d353d35,0xbc483d7b,0xbd6d3cc4,0xbd55bd0e,0xbd800000,0xbd0ebd55,0x3cc4bd6d,0x3d7bbc48,0xbd353d35,0xbd7bbc48,0xbcc4bd6d,0x3d0ebd55,0x8000bd80,0x3d55bd0e,0x3d6d3cc4,0x3c483d7b,
0x3d800000,0x3cc43d6d,0xbd353d35,0xbd6dbcc4,0x8000bd80,0x3d6dbcc4,0x3d353d35,0xbcc43d6d,0xbd800000,0xbcc4bd6d,0x3d35bd35,0x3d6d3cc4,0x80003d80,0xbd6d3cc4,0xbd35bd35,0x3cc4bd6d,
0x3d800000,0x3cc43d6d,0xbd353d35,0xbd6dbcc4,0x8000bd80,0x3d6dbcc4,0x3d353d35,0xbcc43d6d,0xbd800000,0xbcc4bd6d,0x3d35bd35,0x3d6d3cc4,0x80003d80,0xbd6d3cc4,0xbd35bd35,0x3cc4bd6d,
0xbd35bd35,0x3d0ebd55,0x3d6d3cc4,0xbc483d7b,0x8000bd80,0x3d7bbc48,0x3cc43d6d,0xbd553d0e,0x3d35bd35,0x3d553d0e,0xbcc43d6d,0xbd7bbc48,0x3d800000,0x3c483d7b,0xbd6d3cc4,0xbd0ebd55,
0x3d353d35,0xbd0e3d55,0xbd6dbcc4,0x3c48bd7b,0x80003d80,0xbd7b3c48,0xbcc4bd6d,0x3d55bd0e,0xbd353d35,0xbd55bd0e,0x3cc4bd6d,0x3d7b3c48,0xbd800000,0xbc48bd7b,0x3d6dbcc4,0x3d0e3d55,
0x3d80,0xbd800000,0xbd80,0x3d800000,0x3d80,0xbd800000,0xbd80,0x3d800000,0x3d80,0xbd800000,0xbd80,0x3d800000,0x3d80,0xbd800000,0xbd80,0x3d800000,
0x3d80,0xbd800000,0xbd80,0x3d800000,0x3d80,0xbd800000,0xbd80,0x3d800000,0x3d80,0xbd800000,0xbd80,0x3d800000,0x3d80,0xbd800000,0xbd80,0x3d800000,
0xbd353d35,0xbd0ebd55,0x3d6dbcc4,0x3c483d7b,0x3d80,0xbd7bbc48,0x3cc4bd6d,0x3d553d0e,0xbd35bd35,0x3d55bd0e,0x3cc43d6d,0xbd7b3c48,0xbd800000,0x3c48bd7b,0x3d6d3cc4,0xbd0e3d55,
0x3d35bd35,0x3d0e3d55,0xbd6d3cc4,0xbc48bd7b,0xbd80,0x3d7b3c48,0xbcc43d6d,0xbd55bd0e,0x3d353d35,0xbd553d0e,0xbcc4bd6d,0x3d7bbc48,0x3d800000,0xbc483d7b,0xbd6dbcc4,0x3d0ebd55,
0xbd80,0x3d6d3cc4,0xbd353d35,0xbcc4bd6d,0x3d800000,0xbcc43d6d,0xbd35bd35,0x3d6dbcc4,0x3d80,0xbd6dbcc4,0x3d35bd35,0x3cc43d6d,0xbd800000,0x3cc4bd6d,0x3d353d35,0xbd6d3cc4,
0xbd80,0x3d6d3cc4,0xbd353d35,0xbcc4bd6d,0x3d800000,0xbcc43d6d,0xbd35bd35,0x3d6dbcc4,0x3d80,0xbd6dbcc4,0x3d35bd35,0x3cc43d6d,0xbd800000,0x3cc4bd6d,0x3d353d35,0xbd6d3cc4,
0xbd353d35,0xbc48bd7b,0x3d6d3cc4,0xbd553d0e,0x3d800000,0xbd0e3d55,0xbcc4bd6d,0x3d7b3c48,0xbd35bd35,0x3d7bbc48,0xbcc43d6d,0xbd0ebd55,0x3d80,0xbd55bd0e,0x3d6dbcc4,0xbc483d7b,
0x3d35bd35,0x3c483d7b,0xbd6dbcc4,0x3d55bd0e,0xbd800000,0x3d0ebd55,0x3cc43d6d,0xbd7bbc48,0x3d353d35,0xbd7b3c48,0x3cc4bd6d,0x3d0e3d55,0xbd80,0x3d553d0e,0xbd6d3cc4,0x3c48bd7b,
0x3d80,0xbd35bd35,0x3d800000,0xbd353d35,0xbd80,0x3d353d35,0xbd800000,0x3d35bd35,0x3d80,0xbd35bd35,0x3d800000,0xbd353d35,0xbd80,0x3d353d35,0xbd800000,0x3d35bd35,
0x3d80,0xbd35bd35,0x3d800000,0xbd353d35,0xbd80,0x3d353d35,0xbd800000,0x3d35bd35,0x3d80,0xbd35bd35,0x3d800000,0xbd353d35,0xbd80,0x3d353d35,0xbd800000,0x3d35bd35,
0xbd353d35,0x3c48bd7b,0x3cc43d6d,0xbd55bd0e,0xbd80,0x3d0e3d55,0xbd6dbcc4,0x3d7bbc48,0xbd35bd35,0x3d7b3c48,0xbd6d3cc4,0x3d0ebd55,0x3d800000,0xbd553d0e,0x3cc4bd6d,0x3c483d7b,
0x3d35bd35,0xbc483d7b,0xbcc4bd6d,0x3d553d0e,0x3d80,0xbd0ebd55,0x3d6d3cc4,0xbd7b3c48,0x3d353d35,0xbd7bbc48,0x3d6dbcc4,0xbd0e3d55,0xbd800000,0x3d55bd0e,0xbcc43d6d,0xbc48bd7b,
0xbd80,0x3cc43d6d,0xbd35bd35,0x3d6d3cc4,0xbd800000,0x3d6dbcc4,0xbd353d35,0x3cc4bd6d,0x3d80,0xbcc4bd6d,0x3d353d35,0xbd6dbcc4,0x3d800000,0xbd6d3cc4,0x3d35bd35,0xbcc43d6d,
0xbd80,0x3cc43d6d,0xbd35bd35,0x3d6d3cc4,0xbd800000,0x3d6dbcc4,0xbd353d35,0x3cc4bd6d,0x3d80,0xbcc4bd6d,0x3d353d35,0xbd6dbcc4,0x3d800000,0xbd6d3cc4,0x3d35bd35,0xbcc43d6d,
0xbd353d35,0x3d0ebd55,0xbcc43d6d,0x3c48bd7b,0xbd800000,0x3d7bbc48,0xbd6d3cc4,0x3d55bd0e,0xbd35bd35,0x3d553d0e,0xbd6dbcc4,0x3d7b3c48,0xbd80,0x3c483d7b,0xbcc4bd6d,0x3d0e3d55,
0x3d35bd35,0xbd0e3d55,0x3cc4bd6d,0xbc483d7b,0x3d800000,0xbd7b3c48,0x3d6dbcc4,0xbd553d0e,0x3d353d35,0xbd55bd0e,0x3d6d3cc4,0xbd7bbc48,0x3d80,0xbc48bd7b,0x3cc43d6d,0xbd0ebd55,
0xbd800000,0x8000bd80,0x3d800000,0x80003d80,0xbd800000,0x8000bd80,0x3d800000,0x80003d80,0xbd800000,0x8000bd80,0x3d800000,0x80003d80,0xbd800000,0x8000bd80,0x3d800000,0x80003d80,
0xbd800000,0x8000bd80,0x3d800000,0x80003d80,0xbd800000,0x8000bd80,0x3d800000,0x80003d80,0xbd800000,0x8000bd80,0x3d800000,0x80003d80,0xbd800000,0x8000bd80,0x3d800000,0x80003d80,
0xbd35bd35,0x3d55bd0e,0x3cc43d6d,0xbd7b3c48,0xbd800000,0x3c48bd7b,0x3d6d3cc4,0xbd0e3d55,0x3d35bd35,0x3d0e3d55,0xbd6d3cc4,0xbc48bd7b,0x8000bd80,0x3d7b3c48,0xbcc43d6d,0xbd55bd0e,
0x3d353d35,0xbd553d0e,0xbcc4bd6d,0x3d7bbc48,0x3d800000,0xbc483d7b,0xbd6dbcc4,0x3d0ebd55,0xbd353d35,0xbd0ebd55,0x3d6dbcc4,0x3c483d7b,0x80003d80,0xbd7bbc48,0x3cc4bd6d,0x3d553d0e,
0x3d800000,0xbcc43d6d,0xbd35bd35,0x3d6dbcc4,0x80003d80,0xbd6dbcc4,0x3d35bd35,0x3cc43d6d,0xbd800000,0x3cc4bd6d,0x3d353d35,0xbd6d3cc4,0x8000bd80,0x3d6d3cc4,0xbd353d35,0xbcc4bd6d,
0x3d800000,0xbcc43d6d,0xbd35bd35,0x3d6dbcc4,0x80003d80,0xbd6dbcc4,0x3d35bd35,0x3cc43d6d,0xbd800000,0x3cc4bd6d,0x3d353d35,0xbd6d3cc4,0x8000bd80,0x3d6d3cc4,0xbd353d35,0xbcc4bd6d,
0xbd35bd35,0x3d7bbc48,0xbcc43d6d,0xbd0ebd55,0x80003d80,0xbd55bd0e,0x3d6dbcc4,0xbc483d7b,0x3d35bd35,0x3c483d7b,0xbd6dbcc4,0x3d55bd0e,0xbd800000,0x3d0ebd55,0x3cc43d6d,0xbd7bbc48,
0x3d353d35,0xbd7b3c48,0x3cc4bd6d,0x3d0e3d55,0x8000bd80,0x3d553d0e,0xbd6d3cc4,0x3c48bd7b,0xbd353d35,0xbc48bd7b,0x3d6d3cc4,0xbd553d0e,0x3d800000,0xbd0e3d55,0xbcc4bd6d,0x3d7b3c48,
0xbd800000,0x3d35bd35,0x80003d80,0xbd35bd35,0x3d800000,0xbd353d35,0x8000bd80,0x3d353d35,0xbd800000,0x3d35bd35,0x80003d80,0xbd35bd35,0x3d800000,0xbd353d35,0x8000bd80,0x3d353d35,
0xbd800000,0x3d35bd35,0x80003d80,0xbd35bd35,0x3d800000,0xbd353d35,0x8000bd80,0x3d353d35,0xbd800000,0x3d35bd35,0x80003d80,0xbd35bd35,0x3d800000,0xbd353d35,0x8000bd80,0x3d353d35,
0xbd35bd35,0x3d7b3c48,0xbd6d3cc4,0x3d0ebd55,0x3d800000,0xbd553d0e,0x3cc4bd6d,0x3c483d7b,0x3d35bd35,0xbc483d7b,0xbcc4bd6d,0x3d553d0e,0x80003d80,0xbd0ebd55,0x3d6d3cc4,0xbd7b3c48,
0x3d353d35,0xbd7bbc48,0x3d6dbcc4,0xbd0e3d55,0xbd800000,0x3d55bd0e,0xbcc43d6d,0xbc48bd7b,0xbd353d35,0x3c48bd7b,0x3cc43d6d,0xbd55bd0e,0x8000bd80,0x3d0e3d55,0xbd6dbcc4,0x3d7bbc48,
0x3d800000,0xbd6d3cc4,0x3d35bd35,0xbcc43d6d,0x8000bd80,0x3cc43d6d,0xbd35bd35,0x3d6d3cc4,0xbd800000,0x3d6dbcc4,0xbd353d35,0x3cc4bd6d,0x80003d80,0xbcc4bd6d,0x3d353d35,0xbd6dbcc4,
0x3d800000,0xbd6d3cc4,0x3d35bd35,0xbcc43d6d,0x8000bd80,0x3cc43d6d,0xbd35bd35,0x3d6d3cc4,0xbd800000,0x3d6dbcc4,0xbd353d35,0x3cc4bd6d,0x80003d80,0xbcc4bd6d,0x3d353d35,0xbd6dbcc4,
0xbd35bd35,0x3d553d0e,0xbd6dbcc4,0x3d7b3c48,0x8000bd80,0x3c483d7b,0xbcc4bd6d,0x3d0e3d55,0x3d35bd35,0xbd0e3d55,0x3cc4bd6d,0xbc483d7b,0x3d800000,0xbd7b3c48,0x3d6dbcc4,0xbd553d0e,
0x3d353d35,0xbd55bd0e,0x3d6d3cc4,0xbd7bbc48,0x80003d80,0xbc48bd7b,0x3cc43d6d,0xbd0ebd55,0xbd353d35,0x3d0ebd55,0xbcc43d6d,0x3c48bd7b,0xbd800000,0x3d7bbc48,0xbd6d3cc4,0x3d55bd0e,
0x3d80,0xbd80,0x3d80,0xbd80,0x3d80,0xbd80,0x3d80,0xbd80,0x3d80,0xbd80,0x3d80,0xbd80,0x3d80,0xbd80,0x3d80,0xbd80,
0x3d80,0xbd80,0x3d80,0xbd80,0x3d80,0xbd80,0x3d80,0xbd80,0x3d80,0xbd80,0x3d80,0xbd80,0x3d80,0xbd80,0x3d80,0xbd80,
0xbd353d35,0x3d55bd0e,0xbd6d3cc4,0x3d7bbc48,0x3d80,0x3c48bd7b,0xbcc43d6d,0x3d0ebd55,0xbd35bd35,0x3d0e3d55,0xbcc4bd6d,0x3c483d7b,0xbd800000,0x3d7b3c48,0xbd6dbcc4,0x3d553d0e,
0x3d35bd35,0xbd553d0e,0x3d6dbcc4,0xbd7b3c48,0xbd80,0xbc483d7b,0x3cc4bd6d,0xbd0e3d55,0x3d353d35,0xbd0ebd55,0x3cc43d6d,0xbc48bd7b,0x3d800000,0xbd7bbc48,0x3d6d3cc4,0xbd55bd0e,
0xbd80,0xbcc43d6d,0x3d35bd35,0xbd6d3cc4,0x3d800000,0xbd6dbcc4,0x3d353d35,0xbcc4bd6d,0x3d80,0x3cc4bd6d,0xbd353d35,0x3d6dbcc4,0xbd800000,0x3d6d3cc4,0xbd35bd35,0x3cc43d6d,
0xbd80,0xbcc43d6d,0x3d35bd35,0xbd6d3cc4,0x3d800000,0xbd6dbcc4,0x3d353d35,0xbcc4bd6d,0x3d80,0x3cc4bd6d,0xbd353d35,0x3d6dbcc4,0xbd800000,0x3d6d3cc4,0xbd35bd35,0x3cc43d6d,
0xbd353d35,0x3d7bbc48,0xbd6dbcc4,0x3d0e3d55,0x3d800000,0xbd55bd0e,0x3cc43d6d,0x3c48bd7b,0xbd35bd35,0x3c483d7b,0x3cc4bd6d,0xbd553d0e,0x3d80,0x3d0ebd55,0xbd6d3cc4,0x3d7b3c48,
0x3d35bd35,0xbd7b3c48,0x3d6d3cc4,0xbd0ebd55,0xbd800000,0x3d553d0e,0xbcc4bd6d,0xbc483d7b,0x3d353d35,0xbc48bd7b,0xbcc43d6d,0x3d55bd0e,0xbd80,0xbd0e3d55,0x3d6dbcc4,0xbd7bbc48,
0x3d80,0x3d35bd35,0xbd800000,0x3d353d35,0xbd80,0xbd353d35,0x3d800000,0xbd35bd35,0x3d80,0x3d35bd35,0xbd800000,0x3d353d35,0xbd80,0xbd353d35,0x3d800000,0xbd35bd35,
0x3d80,0x3d35bd35,0xbd800000,0x3d353d35,0xbd80,0xbd353d35,0x3d800000,0xbd35bd35,0x3d80,0x3d35bd35,0xbd800000,0x3d353d35,0xbd80,0xbd353d35,0x3d800000,0xbd35bd35,
0xbd353d35,0x3d7b3c48,0xbcc4bd6d,0xbd0e3d55,0xbd80,0xbd553d0e,0x3d6d3cc4,0xbc48bd7b,0xbd35bd35,0xbc483d7b,0x3d6dbcc4,0xbd55bd0e,0x3d800000,0xbd0ebd55,0xbcc43d6d,0x3d7bbc48,
0x3d35bd35,0xbd7bbc48,0x3cc43d6d,0x3d0ebd55,0x3d80,0x3d55bd0e,0xbd6dbcc4,0x3c483d7b,0x3d353d35,0x3c48bd7b,0xbd6d3cc4,0x3d553d0e,0xbd800000,0x3d0e3d55,0x3cc4bd6d,0xbd7b3c48,
0xbd80,0xbd6d3cc4,0x3d353d35,0x3cc4bd6d,0xbd800000,0x3cc43d6d,0x3d35bd35,0xbd6dbcc4,0x3d80,0x3d6dbcc4,0xbd35bd35,0xbcc43d6d,0x3d800000,0xbcc4bd6d,0xbd353d35,0x3d6d3cc4,
0xbd80,0xbd6d3cc4,0x3d353d35,0x3cc4bd6d,0xbd800000,0x3cc43d6d,0x3d35bd35,0xbd6dbcc4,0x3d80,0x3d6dbcc4,0xbd35bd35,0xbcc43d6d,0x3d800000,0xbcc4bd6d,0xbd353d35,0x3d6d3cc4,
0xbd353d35,0x3d553d0e,0x3cc4bd6d,0xbd7bbc48,0xbd800000,0x3c483d7b,0x3d6dbcc4,0xbd0ebd55,0xbd35bd35,0xbd0e3d55,0x3d6d3cc4,0x3c48bd7b,0xbd80,0xbd7b3c48,0x3cc43d6d,0x3d55bd0e,
0x3d35bd35,0xbd55bd0e,0xbcc43d6d,0x3d7b3c48,0x3d800000,0xbc48bd7b,0xbd6d3cc4,0x3d0e3d55,0x3d353d35,0x3d0ebd55,0xbd6dbcc4,0xbc483d7b,0x3d80,0x3d7bbc48,0xbcc4bd6d,0xbd553d0e,
0xbd800000,0x3d800000,0xbd800000,0x3d800000,0xbd800000,0x3d800000,0xbd800000,0x3d800000,0xbd800000,0x3d800000,0xbd800000,0x3d800000,0xbd800000,0x3d800000,0xbd800000,0x3d800000,
0xbd800000,0x3d800000,0xbd800000,0x3d800000,0xbd800000,0x3d800000,0xbd800000,0x3d800000,0xbd800000,0x3d800000,0xbd800000,0x3d800000,0xbd800000,0x3d800000,0xbd800000,0x3d800000,
0xbd35bd35,0x3d0e3d55,0xbcc4bd6d,0x3c483d7b,0xbd800000,0x3d7b3c48,0xbd6dbcc4,0x3d553d0e,0x3d35bd35,0xbd553d0e,0x3d6dbcc4,0xbd7b3c48,0x8000bd80,0xbc483d7b,0x3cc4bd6d,0xbd0e3d55,
0x3d353d35,0xbd0ebd55,0x3cc43d6d,0xbc48bd7b,0x3d800000,0xbd7bbc48,0x3d6d3cc4,0xbd55bd0e,0xbd353d35,0x3d55bd0e,0xbd6d3cc4,0x3d7bbc48,0x80003d80,0x3c48bd7b,0xbcc43d6d,0x3d0ebd55,
0x3d800000,0xbd6dbcc4,0x3d353d35,0xbcc4bd6d,0x80003d80,0x3cc4bd6d,0xbd353d35,0x3d6dbcc4,0xbd800000,0x3d6d3cc4,0xbd35bd35,0x3cc43d6d,0x8000bd80,0xbcc43d6d,0x3d35bd35,0xbd6d3cc4,
0x3d800000,0xbd6dbcc4,0x3d353d35,0xbcc4bd6d,0x80003d80,0x3cc4bd6d,0xbd353d35,0x3d6dbcc4,0xbd800000,0x3d6d3cc4,0xbd35bd35,0x3cc43d6d,0x8000bd80,0xbcc43d6d,0x3d35bd35,0xbd6d3cc4,
0xbd35bd35,0x3c483d7b,0x3cc4bd6d,0xbd553d0e,0x80003d80,0x3d0ebd55,0xbd6d3cc4,0x3d7b3c48,0x3d35bd35,0xbd7b3c48,0x3d6d3cc4,0xbd0ebd55,0xbd800000,0x3d553d0e,0xbcc4bd6d,0xbc483d7b,
0x3d353d35,0xbc48bd7b,0xbcc43d6d,0x3d55bd0e,0x8000bd80,0xbd0e3d55,0x3d6dbcc4,0xbd7bbc48,0xbd353d35,0x3d7bbc48,0xbd6dbcc4,0x3d0e3d55,0x3d800000,0xbd55bd0e,0x3cc43d6d,0x3c48bd7b,
0xbd800000,0x3d353d35,0x8000bd80,0xbd353d35,0x3d800000,0xbd35bd35,0x80003d80,0x3d35bd35,0xbd800000,0x3d353d35,0x8000bd80,0xbd353d35,0x3d800000,0xbd35bd35,0x80003d80,0x3d35bd35,
0xbd800000,0x3d353d35,0x8000bd80,0xbd353d35,0x3d800000,0xbd35bd35,0x80003d80,0x3d35bd35,0xbd800000,0x3d353d35,0x8000bd80,0xbd353d35,0x3d800000,0xbd35bd35,0x80003d80,0x3d35bd35,
0xbd35bd35,0xbc483d7b,0x3d6dbcc4,0xbd55bd0e,0x3d800000,0xbd0ebd55,0xbcc43d6d,0x3d7bbc48,0x3d35bd35,0xbd7bbc48,0x3cc43d6d,0x3d0ebd55,0x80003d80,0x3d55bd0e,0xbd6dbcc4,0x3c483d7b,
0x3d353d35,0x3c48bd7b,0xbd6d3cc4,0x3d553d0e,0xbd800000,0x3d0e3d55,0x3cc4bd6d,0xbd7b3c48,0xbd353d35,0x3d7b3c48,0xbcc4bd6d,0xbd0e3d55,0x8000bd80,0xbd553d0e,0x3d6d3cc4,0xbc48bd7b,
0x3d800000,0xbcc4bd6d,0xbd353d35,0x3d6d3cc4,0x8000bd80,0xbd6d3cc4,0x3d353d35,0x3cc4bd6d,0xbd800000,0x3cc43d6d,0x3d35bd35,0xbd6dbcc4,0x80003d80,0x3d6dbcc4,0xbd35bd35,0xbcc43d6d,
0x3d800000,0xbcc4bd6d,0xbd353d35,0x3d6d3cc4,0x8000bd80,0xbd6d3cc4,0x3d353d35,0x3cc4bd6d,0xbd800000,0x3cc43d6d,0x3d35bd35,0xbd6dbcc4,0x80003d80,0x3d6dbcc4,0xbd35bd35,0xbcc43d6d,
0xbd35bd35,0xbd0e3d55,0x3d6d3cc4,0x3c48bd7b,0x8000bd80,0xbd7b3c48,0x3cc43d6d,0x3d55bd0e,0x3d35bd35,0xbd55bd0e,0xbcc43d6d,0x3d7b3c48,0x3d800000,0xbc48bd7b,0xbd6d3cc4,0x3d0e3d55,
0x3d353d35,0x3d0ebd55,0xbd6dbcc4,0xbc483d7b,0x80003d80,0x3d7bbc48,0xbcc4bd6d,0xbd553d0e,0xbd353d35,0x3d553d0e,0x3cc4bd6d,0xbd7bbc48,0xbd800000,0x3c483d7b,0x3d6dbcc4,0xbd0ebd55,
0x3d80,0x3d800000,0xbd80,0xbd800000,0x3d80,0x3d800000,0xbd80,0xbd800000,0x3d80,0x3d800000,0xbd80,0xbd800000,0x3d80,0x3d800000,0xbd80,0xbd800000,
0x3d80,0x3d800000,0xbd80,0xbd800000,0x3d80,0x3d800000,0xbd80,0xbd800000,0x3d80,0x3d800000,0xbd80,0xbd800000,0x3d80,0x3d800000,0xbd80,0xbd800000,
0xbd353d35,0x3d0e3d55,0x3d6dbcc4,0xbc48bd7b,0x3d80,0x3d7b3c48,0x3cc4bd6d,0xbd55bd0e,0xbd35bd35,0xbd553d0e,0x3cc43d6d,0x3d7bbc48,0xbd800000,0xbc483d7b,0x3d6d3cc4,0x3d0ebd55,
0x3d35bd35,0xbd0ebd55,0xbd6d3cc4,0x3c483d7b,0xbd80,0xbd7bbc48,0xbcc43d6d,0x3d553d0e,0x3d353d35,0x3d55bd0e,0xbcc4bd6d,0xbd7b3c48,0x3d800000,0x3c48bd7b,0xbd6dbcc4,0xbd0e3d55,
0xbd80,0xbd6dbcc4,0xbd353d35,0x3cc43d6d,0x3d800000,0x3cc4bd6d,0xbd35bd35,0xbd6d3cc4,0x3d80,0x3d6d3cc4,0x3d35bd35,0xbcc4bd6d,0xbd800000,0xbcc43d6d,0x3d353d35,0x3d6dbcc4,
0xbd80,0xbd6dbcc4,0xbd353d35,0x3cc43d6d,0x3d800000,0x3cc4bd6d,0xbd35bd35,0xbd6d3cc4,0x3d80,0x3d6d3cc4,0x3d35bd35,0xbcc4bd6d,0xbd800000,0xbcc43d6d,0x3d353d35,0x3d6dbcc4,
0xbd353d35,0x3c483d7b,0x3d6d3cc4,0x3d55bd0e,0x3d800000,0x3d0ebd55,0xbcc4bd6d,0xbd7bbc48,0xbd35bd35,0xbd7b3c48,0xbcc43d6d,0x3d0e3d55,0x3d80,0x3d553d0e,0x3d6dbcc4,0x3c48bd7b,
0x3d35bd35,0xbc48bd7b,0xbd6dbcc4,0xbd553d0e,0xbd800000,0xbd0e3d55,0x3cc43d6d,0x3d7b3c48,0x3d353d35,0x3d7bbc48,0x3cc4bd6d,0xbd0ebd55,0xbd80,0xbd55bd0e,0xbd6d3cc4,0xbc483d7b,
0x3d80,0x3d353d35,0x3d800000,0x3d35bd35,0xbd80,0xbd35bd35,0xbd800000,0xbd353d35,0x3d80,0x3d353d35,0x3d800000,0x3d35bd35,0xbd80,0xbd35bd35,0xbd800000,0xbd353d35,
0x3d80,0x3d353d35,0x3d800000,0x3d35bd35,0xbd80,0xbd35bd35,0xbd800000,0xbd353d35,0x3d80,0x3d353d35,0x3d800000,0x3d35bd35,0xbd80,0xbd35bd35,0xbd800000,0xbd353d35,
0xbd353d35,0xbc483d7b,0x3cc43d6d,0x3d553d0e,0xbd80,0xbd0ebd55,0xbd6dbcc4,0xbd7b3c48,0xbd35bd35,0xbd7bbc48,0xbd6d3cc4,0xbd0e3d55,0x3d800000,0x3d55bd0e,0x3cc4bd6d,0xbc48bd7b,
0x3d35bd35,0x3c48bd7b,0xbcc4bd6d,0xbd55bd0e,0x3d80,0x3d0e3d55,0x3d6d3cc4,0x3d7bbc48,0x3d353d35,0x3d7b3c48,0x3d6dbcc4,0x3d0ebd55,0xbd800000,0xbd553d0e,0xbcc43d6d,0x3c483d7b,
0xbd80,0xbcc4bd6d,0xbd35bd35,0xbd6dbcc4,0xbd800000,0xbd6d3cc4,0xbd353d35,0xbcc43d6d,0x3d80,0x3cc43d6d,0x3d353d35,0x3d6d3cc4,0x3d800000,0x3d6dbcc4,0x3d35bd35,0x3cc4bd6d,
0xbd80,0xbcc4bd6d,0xbd35bd35,0xbd6dbcc4,0xbd800000,0xbd6d3cc4,0xbd353d35,0xbcc43d6d,0x3d80,0x3cc43d6d,0x3d353d35,0x3d6d3cc4,0x3d800000,0x3d6dbcc4,0x3d35bd35,0x3cc4bd6d,
0xbd353d35,0xbd0e3d55,0xbcc43d6d,0xbc483d7b,0xbd800000,0xbd7b3c48,0xbd6d3cc4,0xbd553d0e,0xbd35bd35,0xbd55bd0e,0xbd6dbcc4,0xbd7bbc48,0xbd80,0xbc48bd7b,0xbcc4bd6d,0xbd0ebd55,
0x3d35bd35,0x3d0ebd55,0x3cc4bd6d,0x3c48bd7b,0x3d800000,0x3d7bbc48,0x3d6dbcc4,0x3d55bd0e,0x3d353d35,0x3d553d0e,0x3d6d3cc4,0x3d7b3c48,0x3d80,0x3c483d7b,0x3cc43d6d,0x3d0e3d55,
0xbd800000,0x80003d80,0x3d800000,0x8000bd80,0xbd800000,0x80003d80,0x3d800000,0x8000bd80,0xbd800000,0x80003d80,0x3d800000,0x8000bd80,0xbd800000,0x80003d80,0x3d800000,0x8000bd80,
0xbd800000,0x80003d80,0x3d800000,0x8000bd80,0xbd800000,0x80003d80,0x3d800000,0x8000bd80,0xbd800000,0x80003d80,0x3d800000,0x8000bd80,0xbd800000,0x80003d80,0x3d800000,0x8000bd80,
0xbd35bd35,0xbd553d0e,0x3cc43d6d,0x3d7bbc48,0xbd800000,0xbc483d7b,0x3d6d3cc4,0x3d0ebd55,0x3d35bd35,0xbd0ebd55,0xbd6d3cc4,0x3c483d7b,0x8000bd80,0xbd7bbc48,0xbcc43d6d,0x3d553d0e,
0x3d353d35,0x3d55bd0e,0xbcc4bd6d,0xbd7b3c48,0x3d800000,0x3c48bd7b,0xbd6dbcc4,0xbd0e3d55,0xbd353d35,0x3d0e3d55,0x3d6dbcc4,0xbc48bd7b,0x80003d80,0x3d7b3c48,0x3cc4bd6d,0xbd55bd0e,
0x3d800000,0x3cc4bd6d,0xbd35bd35,0xbd6d3cc4,0x80003d80,0x3d6d3cc4,0x3d35bd35,0xbcc4bd6d,0xbd800000,0xbcc43d6d,0x3d353d35,0x3d6dbcc4,0x8000bd80,0xbd6dbcc4,0xbd353d35,0x3cc43d6d,
0x3d800000,0x3cc4bd6d,0xbd35bd35,0xbd6d3cc4,0x80003d80,0x3d6d3cc4,0x3d35bd35,0xbcc4bd6d,0xbd800000,0xbcc43d6d,0x3d353d35,0x3d6dbcc4,0x8000bd80,0xbd6dbcc4,0xbd353d35,0x3cc43d6d,
0xbd35bd35,0xbd7b3c48,0xbcc43d6d,0x3d0e3d55,0x80003d80,0x3d553d0e,0x3d6dbcc4,0x3c48bd7b,0x3d35bd35,0xbc48bd7b,0xbd6dbcc4,0xbd553d0e,0xbd800000,0xbd0e3d55,0x3cc43d6d,0x3d7b3c48,
0x3d353d35,0x3d7bbc48,0x3cc4bd6d,0xbd0ebd55,0x8000bd80,0xbd55bd0e,0xbd6d3cc4,0xbc483d7b,0xbd353d35,0x3c483d7b,0x3d6d3cc4,0x3d55bd0e,0x3d800000,0x3d0ebd55,0xbcc4bd6d,0xbd7bbc48,
0xbd800000,0xbd353d35,0x80003d80,0x3d353d35,0x3d800000,0x3d35bd35,0x8000bd80,0xbd35bd35,0xbd800000,0xbd353d35,0x80003d80,0x3d353d35,0x3d800000,0x3d35bd35,0x8000bd80,0xbd35bd35,
0xbd800000,0xbd353d35,0x80003d80,0x3d353d35,0x3d800000,0x3d35bd35,0x8000bd80,0xbd35bd35,0xbd800000,0xbd353d35,0x80003d80,0x3d353d35,0x3d800000,0x3d35bd35,0x8000bd80,0xbd35bd35,
0xbd35bd35,0xbd7bbc48,0xbd6d3cc4,0xbd0e3d55,0x3d800000,0x3d55bd0e,0x3cc4bd6d,0xbc48bd7b,0x3d35bd35,0x3c48bd7b,0xbcc4bd6d,0xbd55bd0e,0x80003d80,0x3d0e3d55,0x3d6d3cc4,0x3d7bbc48,
0x3d353d35,0x3d7b3c48,0x3d6dbcc4,0x3d0ebd55,0xbd800000,0xbd553d0e,0xbcc43d6d,0x3c483d7b,0xbd353d35,0xbc483d7b,0x3cc43d6d,0x3d553d0e,0x8000bd80,0xbd0ebd55,0xbd6dbcc4,0xbd7b3c48,
0x3d800000,0x3d6dbcc4,0x3d35bd35,0x3cc4bd6d,0x8000bd80,0xbcc4bd6d,0xbd35bd35,0xbd6dbcc4,0xbd800000,0xbd6d3cc4,0xbd353d35,0xbcc43d6d,0x80003d80,0x3cc43d6d,0x3d353d35,0x3d6d3cc4,
0x3d800000,0x3d6dbcc4,0x3d35bd35,0x3cc4bd6d,0x8000bd80,0xbcc4bd6d,0xbd35bd35,0xbd6dbcc4,0xbd800000,0xbd6d3cc4,0xbd353d35,0xbcc43d6d,0x80003d80,0x3cc43d6d,0x3d353d35,0x3d6d3cc4,
0xbd35bd35,0xbd55bd0e,0xbd6dbcc4,0xbd7bbc48,0x8000bd80,0xbc48bd7b,0xbcc4bd6d,0xbd0ebd55,0x3d35bd35,0x3d0ebd55,0x3cc4bd6d,0x3c48bd7b,0x3d800000,0x3d7bbc48,0x3d6dbcc4,0x3d55bd0e,
0x3d353d35,0x3d553d0e,0x3d6d3cc4,0x3d7b3c48,0x80003d80,0x3c483d7b,0x3cc43d6d,0x3d0e3d55,0xbd353d35,0xbd0e3d55,0xbcc43d6d,0xbc483d7b,0xbd800000,0xbd7b3c48,0xbd6d3cc4,0xbd553d0e,
0x3d80,0xbb493d80,0xbbc93d7f,0xbc163d7d,0xbc483d7b,0xbc793d78,0xbc953d75,0xbcac3d71,0xbcc43d6d,0xbcdb3d67,0xbcf13d62,0xbd043d5c,0xbd0e3d55,0xbd183d4e,0xbd223d46,0xbd2c3d3e,
0xbd353d35,0xbd3e3d2c,0xbd463d22,0xbd4e3d18,0xbd553d0e,0xbd5c3d04,0xbd623cf1,0xbd673cdb,0xbd6d3cc4,0xbd713cac,0xbd753c95,0xbd783c79,0xbd7b3c48,0xbd7d3c16,0xbd7f3bc9,0xbd803b49,
0xbd553d0e,0xbd713cac,0xbd7f3bc9,0xbd7dbc16,0x3d80,0xbc793d78,0xbcf13d62,0xbd2c3d3e,0xbc48bd7b,0x3b49bd80,0x3c95bd75,0x3d04bd5c,0xbd6dbcc4,0xbd4ebd18,0xbd22bd46,0xbcdbbd67,
0x3d7b3c48,0x3d673cdb,0x3d463d22,0x3d183d4e,0x3d35bd35,0x3d5cbd04,0x3d75bc95,0x3d80bb49,0xbd0e3d55,0xbd3e3d2c,0xbd623cf1,0xbd783c79,0x3cc43d6d,0x3c163d7d,0xbbc93d7f,0xbcac3d71,
0x3cc4bd6d,0x3d3ebd2c,0x3d75bc95,0x3d7d3c16,0x3d553d0e,0x3d043d5c,0x3bc93d7f,0xbcac3d71,0x3d80,0xbcdb3d67,0xbd463d22,0xbd783c79,0xbd7bbc48,0xbd4ebd18,0xbcf1bd62,0xbb49bd80,
0x3d6dbcc4,0x3d803b49,0x3d623cf1,0x3d183d4e,0x3c483d7b,0xbc793d78,0xbd223d46,0xbd673cdb,0xbd353d35,0xbd713cac,0xbd7fbbc9,0xbd5cbd04,0xbd0ebd55,0xbc16bd7d,0x3c95bd75,0x3d2cbd3e,
0xbd7b3c48,0xbd67bcdb,0xbcf1bd62,0x3c16bd7d,0x3d6d3cc4,0x3d043d5c,0xbbc93d7f,0xbd2c3d3e,0xbd0ebd55,0x3b49bd80,0x3d22bd46,0x3d78bc79,0x3d80,0xbd183d4e,0xbd753c95,0xbd71bcac,
0x3d553d0e,0x3cac3d71,0xbc953d75,0xbd4e3d18,0xbcc4bd6d,0x3c79bd78,0x3d46bd22,0x3d80bb49,0xbc483d7b,0xbd3e3d2c,0xbd7f3bc9,0xbd5cbd04,0x3d35bd35,0x3d7dbc16,0x3d623cf1,0x3cdb3d67,
0xbd353d35,0xbd80bb49,0xbd22bd46,0x3c16bd7d,0x3d55bd0e,0x3d783c79,0x3cf13d62,0xbcac3d71,0xbd6d3cc4,0xbd67bcdb,0xbc95bd75,0x3d04bd5c,0x3d7bbc48,0x3d4e3d18,0x3bc93d7f,0xbd2c3d3e,
0x3d80,0xbd3e3d2c,0xbd7fbbc9,0xbd18bd4e,0x3c48bd7b,0x3d5cbd04,0x3d753c95,0x3cdb3d67,0xbcc43d6d,0xbd713cac,0xbd62bcf1,0xbc79bd78,0x3d0ebd55,0x3d7dbc16,0x3d463d22,0x3b493d80,
0xbd7bbc48,0xbcacbd71,0x3d22bd46,0x3d7d3c16,0x3d35bd35,0x3d783c79,0x3c953d75,0xbd2c3d3e,0x3d0ebd55,0x3d803b49,0x3cf13d62,0xbd043d5c,0x3cc43d6d,0xbd183d4e,0xbd7fbbc9,0xbcdbbd67,
0x3d55bd0e,0x3d673cdb,0x3bc93d7f,0xbd4e3d18,0x3d80,0xbd5c3d04,0xbd62bcf1,0xbb49bd80,0x3c483d7b,0xbd3e3d2c,0xbd75bc95,0xbc79bd78,0xbd6dbcc4,0xbc16bd7d,0x3d46bd22,0x3d713cac,
0x3d6dbcc4,0x3d2c3d3e,0xbcf13d62,0xbd7dbc16,0xbc48bd7b,0x3d5cbd04,0x3d463d22,0xbcac3d71,0xbd353d35,0xbd67bcdb,0x3bc9bd7f,0x3d78bc79,0x3d0e3d55,0xbd183d4e,0xbd75bc95,0xbb49bd80,
0x3cc4bd6d,0x3d803b49,0x3c953d75,0xbd4e3d18,0xbd55bd0e,0x3c79bd78,0x3d7fbbc9,0x3cdb3d67,0x3d80,0xbd713cac,0xbd22bd46,0x3d04bd5c,0x3d7b3c48,0x3c163d7d,0xbd623cf1,0xbd3ebd2c,
0xbd55bd0e,0x3cdbbd67,0x3d753c95,0xbc163d7d,0xbcc4bd6d,0x3d5cbd04,0x3d223d46,0xbd2c3d3e,0x3c48bd7b,0x3d803b49,0x3bc93d7f,0xbd783c79,0x3d35bd35,0x3d4e3d18,0xbcf13d62,0xbd71bcac,
0x3d7bbc48,0x3cac3d71,0xbd623cf1,0xbd18bd4e,0x3d6d3cc4,0xbc793d78,0xbd7fbbc9,0xbb49bd80,0x3d0e3d55,0xbd3e3d2c,0xbd46bd22,0x3d04bd5c,0x3d80,0xbd7d3c16,0xbc95bd75,0x3d67bcdb,
0xbd800000,0xbd80bb49,0xbd7fbbc9,0xbd7dbc16,0xbd7bbc48,0xbd78bc79,0xbd75bc95,0xbd71bcac,0xbd6dbcc4,0xbd67bcdb,0xbd62bcf1,0xbd5cbd04,0xbd55bd0e,0xbd4ebd18,0xbd46bd22,0xbd3ebd2c,
0xbd35bd35,0xbd2cbd3e,0xbd22bd46,0xbd18bd4e,0xbd0ebd55,0xbd04bd5c,0xbcf1bd62,0xbcdbbd67,0xbcc4bd6d,0xbcacbd71,0xbc95bd75,0xbc79bd78,0xbc48bd7b,0xbc16bd7d,0xbbc9bd7f,0xbb49bd80,
0xbd0ebd55,0xbcacbd71,0xbbc9bd7f,0x3c16bd7d,0xbd800000,0xbd78bc79,0xbd62bcf1,0xbd3ebd2c,0x3d7bbc48,0x3d803b49,0x3d753c95,0x3d5c3d04,0x3cc4bd6d,0x3d18bd4e,0x3d46bd22,0x3d67bcdb,
0xbc483d7b,0xbcdb3d67,0xbd223d46,0xbd4e3d18,0x3d353d35,0x3d043d5c,0x3c953d75,0x3b493d80,0xbd55bd0e,0xbd2cbd3e,0xbcf1bd62,0xbc79bd78,0xbd6d3cc4,0xbd7d3c16,0xbd7fbbc9,0xbd71bcac,
0x3d6d3cc4,0x3d2c3d3e,0x3c953d75,0xbc163d7d,0xbd0e3d55,0xbd5c3d04,0xbd7f3bc9,0xbd71bcac,0xbd800000,0xbd67bcdb,0xbd22bd46,0xbc79bd78,0x3c48bd7b,0x3d18bd4e,0x3d62bcf1,0x3d80bb49,
0x3cc43d6d,0xbb493d80,0xbcf13d62,0xbd4e3d18,0xbd7b3c48,0xbd78bc79,0xbd46bd22,0xbcdbbd67,0xbd35bd35,0xbcacbd71,0x3bc9bd7f,0x3d04bd5c,0x3d55bd0e,0x3d7dbc16,0x3d753c95,0x3d3e3d2c,
0xbc48bd7b,0x3cdbbd67,0x3d62bcf1,0x3d7d3c16,0xbcc43d6d,0xbd5c3d04,0xbd7fbbc9,0xbd3ebd2c,0x3d55bd0e,0x3d803b49,0x3d463d22,0x3c793d78,0xbd800000,0xbd4ebd18,0xbc95bd75,0x3cacbd71,
0xbd0e3d55,0xbd713cac,0xbd75bc95,0xbd18bd4e,0x3d6dbcc4,0x3d783c79,0x3d223d46,0x3b493d80,0xbd7bbc48,0xbd2cbd3e,0xbbc9bd7f,0x3d04bd5c,0x3d353d35,0x3c163d7d,0xbcf13d62,0xbd673cdb,
0xbd35bd35,0x3b49bd80,0x3d46bd22,0x3d7d3c16,0x3d0e3d55,0xbc793d78,0xbd623cf1,0xbd71bcac,0xbcc4bd6d,0x3cdbbd67,0x3d75bc95,0x3d5c3d04,0x3c483d7b,0xbd183d4e,0xbd7f3bc9,0xbd3ebd2c,
0xbd800000,0xbd2cbd3e,0x3bc9bd7f,0x3d4ebd18,0x3d7b3c48,0x3d043d5c,0xbc953d75,0xbd673cdb,0xbd6dbcc4,0xbcacbd71,0x3cf1bd62,0x3d78bc79,0x3d553d0e,0x3c163d7d,0xbd223d46,0xbd803b49,
0x3c48bd7b,0x3d71bcac,0x3d463d22,0xbc163d7d,0x3d353d35,0xbc793d78,0xbd753c95,0xbd3ebd2c,0x3d553d0e,0xbb493d80,0xbd623cf1,0xbd5cbd04,0xbd6d3cc4,0xbd4ebd18,0x3bc9bd7f,0x3d67bcdb,
0x3d0e3d55,0xbcdb3d67,0xbd7f3bc9,0xbd18bd4e,0xbd800000,0xbd04bd5c,0x3cf1bd62,0x3d80bb49,0xbd7b3c48,0xbd2cbd3e,0x3c95bd75,0x3d78bc79,0x3cc4bd6d,0x3d7dbc16,0x3d223d46,0xbcac3d71,
0x3cc43d6d,0xbd3e3d2c,0xbd62bcf1,0x3c16bd7d,0x3d7bbc48,0x3d043d5c,0xbd223d46,0xbd71bcac,0xbd35bd35,0x3cdbbd67,0x3d7f3bc9,0x3c793d78,0xbd553d0e,0xbd4ebd18,0x3c95bd75,0x3d80bb49,
0x3d6d3cc4,0xbb493d80,0xbd753c95,0xbd18bd4e,0x3d0ebd55,0x3d783c79,0x3bc93d7f,0xbd673cdb,0xbd800000,0xbcacbd71,0x3d46bd22,0x3d5c3d04,0xbc483d7b,0xbd7d3c16,0xbcf1bd62,0x3d2cbd3e,
0x3d0ebd55,0x3d673cdb,0xbc953d75,0xbd7dbc16,0x3d6dbcc4,0x3d043d5c,0xbd463d22,0xbd3ebd2c,0x3d7b3c48,0xbb493d80,0xbd7f3bc9,0xbc79bd78,0x3d353d35,0xbd183d4e,0xbd62bcf1,0x3cacbd71,
0x3c483d7b,0xbd713cac,0xbcf1bd62,0x3d4ebd18,0xbcc43d6d,0xbd78bc79,0x3bc9bd7f,0x3d80bb49,0xbd553d0e,0xbd2cbd3e,0x3d22bd46,0x3d5c3d04,0xbd800000,0xbc16bd7d,0x3d75bc95,0x3cdb3d67,
0x3d80,0xbd80bb49,0x3bc9bd7f,0x3d7d3c16,0xbc483d7b,0xbd78bc79,0x3c95bd75,0x3d713cac,0xbcc43d6d,0xbd67bcdb,0x3cf1bd62,0x3d5c3d04,0xbd0e3d55,0xbd4ebd18,0x3d22bd46,0x3d3e3d2c,
0xbd353d35,0xbd2cbd3e,0x3d46bd22,0x3d183d4e,0xbd553d0e,0xbd04bd5c,0x3d62bcf1,0x3cdb3d67,0xbd6d3cc4,0xbcacbd71,0x3d75bc95,0x3c793d78,0xbd7b3c48,0xbc16bd7d,0x3d7fbbc9,0x3b493d80,
0xbd553d0e,0xbcacbd71,0x3d7fbbc9,0xbc163d7d,0x3d80,0xbd78bc79,0x3cf1bd62,0x3d3e3d2c,0xbc48bd7b,0x3d803b49,0xbc953d75,0xbd5cbd04,0xbd6dbcc4,0x3d18bd4e,0x3d223d46,0xbd673cdb,
0x3d7b3c48,0xbcdb3d67,0xbd46bd22,0x3d4ebd18,0x3d35bd35,0x3d043d5c,0xbd753c95,0xbb49bd80,0xbd0e3d55,0xbd2cbd3e,0x3d62bcf1,0x3c793d78,0x3cc43d6d,0xbd7d3c16,0x3bc9bd7f,0x3d713cac,
0x3cc4bd6d,0x3d2c3d3e,0xbd753c95,0x3c16bd7d,0x3d553d0e,0xbd5c3d04,0xbbc9bd7f,0x3d713cac,0x3d80,0xbd67bcdb,0x3d46bd22,0x3c793d78,0xbd7bbc48,0x3d18bd4e,0x3cf13d62,0xbd803b49,
0x3d6dbcc4,0xbb493d80,0xbd62bcf1,0x3d4ebd18,0x3c483d7b,0xbd78bc79,0x3d22bd46,0x3cdb3d67,0xbd353d35,0xbcacbd71,0x3d7f3bc9,0xbd043d5c,0xbd0ebd55,0x3d7dbc16,0xbc953d75,0xbd3ebd2c,
0xbd7b3c48,0x3cdbbd67,0x3cf13d62,0xbd7dbc16,0x3d6d3cc4,0xbd5c3d04,0x3bc9bd7f,0x3d3e3d2c,0xbd0ebd55,0x3d803b49,0xbd223d46,0xbc79bd78,0x3d80,0xbd4ebd18,0x3d75bc95,0xbcac3d71,
0x3d553d0e,0xbd713cac,0x3c95bd75,0x3d183d4e,0xbcc4bd6d,0x3d783c79,0xbd463d22,0xbb49bd80,0xbc483d7b,0xbd2cbd3e,0x3d7fbbc9,0xbd043d5c,0x3d35bd35,0x3c163d7d,0xbd62bcf1,0x3d67bcdb,
0xbd353d35,0x3b49bd80,0x3d223d46,0xbd7dbc16,0x3d55bd0e,0xbc793d78,0xbcf1bd62,0x3d713cac,0xbd6d3cc4,0x3cdbbd67,0x3c953d75,0xbd5cbd04,0x3d7bbc48,0xbd183d4e,0xbbc9bd7f,0x3d3e3d2c,
0x3d80,0xbd2cbd3e,0x3d7f3bc9,0xbd4e3d18,0x3c48bd7b,0x3d043d5c,0xbd75bc95,0x3d67bcdb,0xbcc43d6d,0xbcacbd71,0x3d623cf1,0xbd783c79,0x3d0ebd55,0x3c163d7d,0xbd46bd22,0x3d80bb49,
0xbd7bbc48,0x3d71bcac,0xbd223d46,0x3c16bd7d,0x3d35bd35,0xbc793d78,0xbc95bd75,0x3d3e3d2c,0x3d0ebd55,0xbb493d80,0xbcf1bd62,0x3d5c3d04,0x3cc43d6d,0xbd4ebd18,0x3d7f3bc9,0xbd673cdb,
0x3d55bd0e,0xbcdb3d67,0xbbc9bd7f,0x3d183d4e,0x3d80,0xbd04bd5c,0x3d623cf1,0xbd803b49,0x3c483d7b,0xbd2cbd3e,0x3d753c95,0xbd783c79,0xbd6dbcc4,0x3d7dbc16,0xbd463d22,0x3cacbd71,
0x3d6dbcc4,0xbd3e3d2c,0x3cf1bd62,0xbc163d7d,0xbc48bd7b,0x3d043d5c,0xbd46bd22,0x3d713cac,0xbd353d35,0x3cdbbd67,0xbbc93d7f,0xbc79bd78,0x3d0e3d55,0xbd4ebd18,0x3d753c95,0xbd803b49,
0x3cc4bd6d,0xbb493d80,0xbc95bd75,0x3d183d4e,0xbd55bd0e,0x3d783c79,0xbd7f3bc9,0x3d67bcdb,0x3d80,0xbcacbd71,0x3d223d46,0xbd5cbd04,0x3d7b3c48,0xbd7d3c16,0x3d62bcf1,0xbd2c3d3e,
0xbd55bd0e,0x3d673cdb,0xbd75bc95,0x3d7d3c16,0xbcc4bd6d,0x3d043d5c,0xbd22bd46,0x3d3e3d2c,0x3c48bd7b,0xbb493d80,0xbbc9bd7f,0x3c793d78,0x3d35bd35,0xbd183d4e,0x3cf1bd62,0xbcac3d71,
0x3d7bbc48,0xbd713cac,0x3d62bcf1,0xbd4e3d18,0x3d6d3cc4,0xbd78bc79,0x3d7f3bc9,0xbd803b49,0x3d0e3d55,0xbd2cbd3e,0x3d463d22,0xbd5cbd04,0x3d80,0xbc16bd7d,0x3c953d75,0xbcdbbd67,
0xbd800000,0x3b49bd80,0x3d7f3bc9,0xbc163d7d,0xbd7bbc48,0x3c79bd78,0x3d753c95,0xbcac3d71,0xbd6dbcc4,0x3cdbbd67,0x3d623cf1,0xbd043d5c,0xbd55bd0e,0x3d18bd4e,0x3d463d22,0xbd2c3d3e,
0xbd35bd35,0x3d3ebd2c,0x3d223d46,0xbd4e3d18,0xbd0ebd55,0x3d5cbd04,0x3cf13d62,0xbd673cdb,0xbcc4bd6d,0x3d71bcac,0x3c953d75,0xbd783c79,0xbc48bd7b,0x3d7dbc16,0x3bc93d7f,0xbd803b49,
0xbd0ebd55,0x3d71bcac,0x3bc93d7f,0xbd7dbc16,0xbd800000,0x3c79bd78,0x3d623cf1,0xbd2c3d3e,0x3d7bbc48,0xbb493d80,0xbd75bc95,0x3d04bd5c,0x3cc4bd6d,0x3d4e3d18,0xbd463d22,0xbcdbbd67,
0xbc483d7b,0xbd67bcdb,0x3d22bd46,0x3d183d4e,0x3d353d35,0xbd5c3d04,0xbc95bd75,0x3d80bb49,0xbd55bd0e,0x3d3ebd2c,0x3cf13d62,0xbd783c79,0xbd6d3cc4,0xbc16bd7d,0x3d7f3bc9,0xbcac3d71,
0x3d6d3cc4,0xbd3e3d2c,0xbc95bd75,0x3d7d3c16,0xbd0e3d55,0xbd04bd5c,0x3d7fbbc9,0xbcac3d71,0xbd800000,0x3cdbbd67,0x3d223d46,0xbd783c79,0x3c48bd7b,0x3d4e3d18,0xbd623cf1,0xbb49bd80,
0x3cc43d6d,0xbd80bb49,0x3cf1bd62,0x3d183d4e,0xbd7b3c48,0x3c79bd78,0x3d463d22,0xbd673cdb,0xbd35bd35,0x3d71bcac,0xbbc93d7f,0xbd5cbd04,0x3d55bd0e,0x3c163d7d,0xbd75bc95,0x3d2cbd3e,
0xbc48bd7b,0x3d673cdb,0xbd623cf1,0x3c16bd7d,0xbcc43d6d,0xbd04bd5c,0x3d7f3bc9,0xbd2c3d3e,0x3d55bd0e,0xbb493d80,0xbd46bd22,0x3d78bc79,0xbd800000,0x3d18bd4e,0x3c953d75,0xbd71bcac,
0xbd0e3d55,0xbcacbd71,0x3d753c95,0xbd4e3d18,0x3d6dbcc4,0xbc793d78,0xbd22bd46,0x3d80bb49,0xbd7bbc48,0x3d3ebd2c,0x3bc93d7f,0xbd5cbd04,0x3d353d35,0xbd7d3c16,0x3cf1bd62,0x3cdb3d67,
0xbd35bd35,0x3d803b49,0xbd463d22,0x3c16bd7d,0x3d0e3d55,0xbd78bc79,0x3d62bcf1,0xbcac3d71,0xbcc4bd6d,0x3d673cdb,0xbd753c95,0x3d04bd5c,0x3c483d7b,0xbd4ebd18,0x3d7fbbc9,0xbd2c3d3e,
0xbd800000,0x3d3ebd2c,0xbbc93d7f,0xbd18bd4e,0x3d7b3c48,0xbd5c3d04,0x3c95bd75,0x3cdb3d67,0xbd6dbcc4,0x3d71bcac,0xbcf13d62,0xbc79bd78,0x3d553d0e,0xbd7d3c16,0x3d22bd46,0x3b493d80,
0x3c48bd7b,0x3cac3d71,0xbd46bd22,0x3d7d3c16,0x3d353d35,0xbd78bc79,0x3d75bc95,0xbd2c3d3e,0x3d553d0e,0xbd80bb49,0x3d62bcf1,0xbd043d5c,0xbd6d3cc4,0x3d18bd4e,0xbbc93d7f,0xbcdbbd67,
0x3d0e3d55,0xbd67bcdb,0x3d7fbbc9,0xbd4e3d18,0xbd800000,0x3d5cbd04,0xbcf13d62,0xbb49bd80,0xbd7b3c48,0x3d3ebd2c,0xbc953d75,0xbc79bd78,0x3cc4bd6d,0x3c163d7d,0xbd22bd46,0x3d713cac,
0x3cc43d6d,0xbd2cbd3e,0x3d623cf1,0xbd7dbc16,0x3d7bbc48,0xbd5c3d04,0x3d22bd46,0xbcac3d71,0xbd35bd35,0x3d673cdb,0xbd7fbbc9,0x3d78bc79,0xbd553d0e,0x3d18bd4e,0xbc953d75,0xbb49bd80,
0x3d6d3cc4,0xbd80bb49,0x3d75bc95,0xbd4e3d18,0x3d0ebd55,0xbc793d78,0xbbc9bd7f,0x3cdb3d67,0xbd800000,0x3d71bcac,0xbd463d22,0x3d04bd5c,0xbc483d7b,0xbc16bd7d,0x3cf13d62,0xbd3ebd2c,
0x3d0ebd55,0xbcdb3d67,0x3c95bd75,0xbc163d7d,0x3d6dbcc4,0xbd5c3d04,0x3d46bd22,0xbd2c3d3e,0x3d7b3c48,0xbd80bb49,0x3d7fbbc9,0xbd783c79,0x3d353d35,0xbd4ebd18,0x3d623cf1,0xbd71bcac,
0x3c483d7b,0xbcacbd71,0x3cf13d62,0xbd18bd4e,0xbcc43d6d,0x3c79bd78,0xbbc93d7f,0xbb49bd80,0xbd553d0e,0x3d3ebd2c,0xbd223d46,0x3d04bd5c,0xbd800000,0x3d7dbc16,0xbd753c95,0x3d67bcdb,
0x3d80,0x3b49bd80,0xbbc93d7f,0x3c16bd7d,0xbc483d7b,0x3c79bd78,0xbc953d75,0x3cacbd71,0xbcc43d6d,0x3cdbbd67,0xbcf13d62,0x3d04bd5c,0xbd0e3d55,0x3d18bd4e,0xbd223d46,0x3d2cbd3e,
0xbd353d35,0x3d3ebd2c,0xbd463d22,0x3d4ebd18,0xbd553d0e,0x3d5cbd04,0xbd623cf1,0x3d67bcdb,0xbd6d3cc4,0x3d71bcac,0xbd753c95,0x3d78bc79,0xbd7b3c48,0x3d7dbc16,0xbd7f3bc9,0x3d80bb49,
0xbd553d0e,0x3d71bcac,0xbd7f3bc9,0x3d7d3c16,0x3d80,0x3c79bd78,0xbcf13d62,0x3d2cbd3e,0xbc48bd7b,0xbb493d80,0x3c95bd75,0xbd043d5c,0xbd6dbcc4,0x3d4e3d18,0xbd22bd46,0x3cdb3d67,
0x3d7b3c48,0xbd67bcdb,0x3d463d22,0xbd18bd4e,0x3d35bd35,0xbd5c3d04,0x3d75bc95,0xbd803b49,0xbd0e3d55,0x3d3ebd2c,0xbd623cf1,0x3d78bc79,0x3cc43d6d,0xbc16bd7d,0xbbc93d7f,0x3cacbd71,
0x3cc4bd6d,0xbd3e3d2c,0x3d75bc95,0xbd7dbc16,0x3d553d0e,0xbd04bd5c,0x3bc93d7f,0x3cacbd71,0x3d80,0x3cdbbd67,0xbd463d22,0x3d78bc79,0xbd7bbc48,0x3d4e3d18,0xbcf1bd62,0x3b493d80,
0x3d6dbcc4,0xbd80bb49,0x3d623cf1,0xbd18bd4e,0x3c483d7b,0x3c79bd78,0xbd223d46,0x3d67bcdb,0xbd353d35,0x3d71bcac,0xbd7fbbc9,0x3d5c3d04,0xbd0ebd55,0x3c163d7d,0x3c95bd75,0xbd2c3d3e,
0xbd7b3c48,0x3d673cdb,0xbcf1bd62,0xbc163d7d,0x3d6d3cc4,0xbd04bd5c,0xbbc93d7f,0x3d2cbd3e,0xbd0ebd55,0xbb493d80,0x3d22bd46,0xbd783c79,0x3d80,0x3d18bd4e,0xbd753c95,0x3d713cac,
0x3d553d0e,0xbcacbd71,0xbc953d75,0x3d4ebd18,0xbcc4bd6d,0xbc793d78,0x3d46bd22,0xbd803b49,0xbc483d7b,0x3d3ebd2c,0xbd7f3bc9,0x3d5c3d04,0x3d35bd35,0xbd7d3c16,0x3d623cf1,0xbcdbbd67,
0xbd353d35,0x3d803b49,0xbd22bd46,0xbc163d7d,0x3d55bd0e,0xbd78bc79,0x3cf13d62,0x3cacbd71,0xbd6d3cc4,0x3d673cdb,0xbc95bd75,0xbd043d5c,0x3d7bbc48,0xbd4ebd18,0x3bc93d7f,0x3d2cbd3e,
0x3d80,0x3d3ebd2c,0xbd7fbbc9,0x3d183d4e,0x3c48bd7b,0xbd5c3d04,0x3d753c95,0xbcdbbd67,0xbcc43d6d,0x3d71bcac,0xbd62bcf1,0x3c793d78,0x3d0ebd55,0xbd7d3c16,0x3d463d22,0xbb49bd80,
0xbd7bbc48,0x3cac3d71,0x3d22bd46,0xbd7dbc16,0x3d35bd35,0xbd78bc79,0x3c953d75,0x3d2cbd3e,0x3d0ebd55,0xbd80bb49,0x3cf13d62,0x3d04bd5c,0x3cc43d6d,0x3d18bd4e,0xbd7fbbc9,0x3cdb3d67,
0x3d55bd0e,0xbd67bcdb,0x3bc93d7f,0x3d4ebd18,0x3d80,0x3d5cbd04,0xbd62bcf1,0x3b493d80,0x3c483d7b,0x3d3ebd2c,0xbd75bc95,0x3c793d78,0xbd6dbcc4,0x3c163d7d,0x3d46bd22,0xbd71bcac,
0x3d6dbcc4,0xbd2cbd3e,0xbcf13d62,0x3d7d3c16,0xbc48bd7b,0xbd5c3d04,0x3d463d22,0x3cacbd71,0xbd353d35,0x3d673cdb,0x3bc9bd7f,0xbd783c79,0x3d0e3d55,0x3d18bd4e,0xbd75bc95,0x3b493d80,
0x3cc4bd6d,0xbd80bb49,0x3c953d75,0x3d4ebd18,0xbd55bd0e,0xbc793d78,0x3d7fbbc9,0xbcdbbd67,0x3d80,0x3d71bcac,0xbd22bd46,0xbd043d5c,0x3d7b3c48,0xbc16bd7d,0xbd623cf1,0x3d3e3d2c,
0xbd55bd0e,0xbcdb3d67,0x3d753c95,0x3c16bd7d,0xbcc4bd6d,0xbd5c3d04,0x3d223d46,0x3d2cbd3e,0x3c48bd7b,0xbd80bb49,0x3bc93d7f,0x3d78bc79,0x3d35bd35,0xbd4ebd18,0xbcf13d62,0x3d713cac,
0x3d7bbc48,0xbcacbd71,0xbd623cf1,0x3d183d4e,0x3d6d3cc4,0x3c79bd78,0xbd7fbbc9,0x3b493d80,0x3d0e3d55,0x3d3ebd2c,0xbd46bd22,0xbd043d5c,0x3d80,0x3d7dbc16,0xbc95bd75,0xbd673cdb,
0xbd800000,0x3d803b49,0xbd7fbbc9,0x3d7d3c16,0xbd7bbc48,0x3d783c79,0xbd75bc95,0x3d713cac,0xbd6dbcc4,0x3d673cdb,0xbd62bcf1,0x3d5c3d04,0xbd55bd0e,0x3d4e3d18,0xbd46bd22,0x3d3e3d2c,
0xbd35bd35,0x3d2c3d3e,0xbd22bd46,0x3d183d4e,0xbd0ebd55,0x3d043d5c,0xbcf1bd62,0x3cdb3d67,0xbcc4bd6d,0x3cac3d71,0xbc95bd75,0x3c793d78,0xbc48bd7b,0x3c163d7d,0xbbc9bd7f,0x3b493d80,
0xbd0ebd55,0x3cac3d71,0xbbc9bd7f,0xbc163d7d,0xbd800000,0x3d783c79,0xbd62bcf1,0x3d3e3d2c,0x3d7bbc48,0xbd80bb49,0x3d753c95,0xbd5cbd04,0x3cc4bd6d,0xbd183d4e,0x3d46bd22,0xbd673cdb,
0xbc483d7b,0x3cdbbd67,0xbd223d46,0x3d4ebd18,0x3d353d35,0xbd04bd5c,0x3c953d75,0xbb49bd80,0xbd55bd0e,0x3d2c3d3e,0xbcf1bd62,0x3c793d78,0xbd6d3cc4,0x3d7dbc16,0xbd7fbbc9,0x3d713cac,
0x3d6d3cc4,0xbd2cbd3e,0x3c953d75,0x3c16bd7d,0xbd0e3d55,0x3d5cbd04,0xbd7f3bc9,0x3d713cac,0xbd800000,0x3d673cdb,0xbd22bd46,0x3c793d78,0x3c48bd7b,0xbd183d4e,0x3d62bcf1,0xbd803b49,
0x3cc43d6d,0x3b49bd80,0xbcf13d62,0x3d4ebd18,0xbd7b3c48,0x3d783c79,0xbd46bd22,0x3cdb3d67,0xbd35bd35,0x3cac3d71,0x3bc9bd7f,0xbd043d5c,0x3d55bd0e,0xbd7d3c16,0x3d753c95,0xbd3ebd2c,
0xbc48bd7b,0xbcdb3d67,0x3d62bcf1,0xbd7dbc16,0xbcc43d6d,0x3d5cbd04,0xbd7fbbc9,0x3d3e3d2c,0x3d55bd0e,0xbd80bb49,0x3d463d22,0xbc79bd78,0xbd800000,0x3d4e3d18,0xbc95bd75,0xbcac3d71,
0xbd0e3d55,0x3d71bcac,0xbd75bc95,0x3d183d4e,0x3d6dbcc4,0xbd78bc79,0x3d223d46,0xbb49bd80,0xbd7bbc48,0x3d2c3d3e,0xbbc9bd7f,0xbd043d5c,0x3d353d35,0xbc16bd7d,0xbcf13d62,0x3d67bcdb,
0xbd35bd35,0xbb493d80,0x3d46bd22,0xbd7dbc16,0x3d0e3d55,0x3c79bd78,0xbd623cf1,0x3d713cac,0xbcc4bd6d,0xbcdb3d67,0x3d75bc95,0xbd5cbd04,0x3c483d7b,0x3d18bd4e,0xbd7f3bc9,0x3d3e3d2c,
0xbd800000,0x3d2c3d3e,0x3bc9bd7f,0xbd4e3d18,0x3d7b3c48,0xbd04bd5c,0xbc953d75,0x3d67bcdb,0xbd6dbcc4,0x3cac3d71,0x3cf1bd62,0xbd783c79,0x3d553d0e,0xbc16bd7d,0xbd223d46,0x3d80bb49,
0x3c48bd7b,0xbd713cac,0x3d463d22,0x3c16bd7d,0x3d353d35,0x3c79bd78,0xbd753c95,0x3d3e3d2c,0x3d553d0e,0x3b49bd80,0xbd623cf1,0x3d5c3d04,0xbd6d3cc4,0x3d4e3d18,0x3bc9bd7f,0xbd673cdb,
0x3d0e3d55,0x3cdbbd67,0xbd7f3bc9,0x3d183d4e,0xbd800000,0x3d043d5c,0x3cf1bd62,0xbd803b49,0xbd7b3c48,0x3d2c3d3e,0x3c95bd75,0xbd783c79,0x3cc4bd6d,0xbd7d3c16,0x3d223d46,0x3cacbd71,
0x3cc43d6d,0x3d3ebd2c,0xbd62bcf1,0xbc163d7d,0x3d7bbc48,0xbd04bd5c,0xbd223d46,0x3d713cac,0xbd35bd35,0xbcdb3d67,0x3d7f3bc9,0xbc79bd78,0xbd553d0e,0x3d4e3d18,0x3c95bd75,0xbd803b49,
0x3d6d3cc4,0x3b49bd80,0xbd753c95,0x3d183d4e,0x3d0ebd55,0xbd78bc79,0x3bc93d7f,0x3d67bcdb,0xbd800000,0x3cac3d71,0x3d46bd22,0xbd5cbd04,0xbc483d7b,0x3d7dbc16,0xbcf1bd62,0xbd2c3d3e,
0x3d0ebd55,0xbd67bcdb,0xbc953d75,0x3d7d3c16,0x3d6dbcc4,0xbd04bd5c,0xbd463d22,0x3d3e3d2c,0x3d7b3c48,0x3b49bd80,0xbd7f3bc9,0x3c793d78,0x3d353d35,0x3d18bd4e,0xbd62bcf1,0xbcac3d71,
0x3c483d7b,0x3d71bcac,0xbcf1bd62,0xbd4e3d18,0xbcc43d6d,0x3d783c79,0x3bc9bd7f,0xbd803b49,0xbd553d0e,0x3d2c3d3e,0x3d22bd46,0xbd5cbd04,0xbd800000,0x3c163d7d,0x3d75bc95,0xbcdbbd67,
0x3d80,0x3d803b49,0x3bc9bd7f,0xbd7dbc16,0xbc483d7b,0x3d783c79,0x3c95bd75,0xbd71bcac,0xbcc43d6d,0x3d673cdb,0x3cf1bd62,0xbd5cbd04,0xbd0e3d55,0x3d4e3d18,0x3d22bd46,0xbd3ebd2c,
0xbd353d35,0x3d2c3d3e,0x3d46bd22,0xbd18bd4e,0xbd553d0e,0x3d043d5c,0x3d62bcf1,0xbcdbbd67,0xbd6d3cc4,0x3cac3d71,0x3d75bc95,0xbc79bd78,0xbd7b3c48,0x3c163d7d,0x3d7fbbc9,0xbb49bd80,
0xbd553d0e,0x3cac3d71,0x3d7fbbc9,0x3c16bd7d,0x3d80,0x3d783c79,0x3cf1bd62,0xbd3ebd2c,0xbc48bd7b,0xbd80bb49,0xbc953d75,0x3d5c3d04,0xbd6dbcc4,0xbd183d4e,0x3d223d46,0x3d67bcdb,
0x3d7b3c48,0x3cdbbd67,0xbd46bd22,0xbd4e3d18,0x3d35bd35,0xbd04bd5c,0xbd753c95,0x3b493d80,0xbd0e3d55,0x3d2c3d3e,0x3d62bcf1,0xbc79bd78,0x3cc43d6d,0x3d7dbc16,0x3bc9bd7f,0xbd71bcac,
0x3cc4bd6d,0xbd2cbd3e,0xbd753c95,0xbc163d7d,0x3d553d0e,0x3d5cbd04,0xbbc9bd7f,0xbd71bcac,0x3d80,0x3d673cdb,0x3d46bd22,0xbc79bd78,0xbd7bbc48,0xbd183d4e,0x3cf13d62,0x3d80bb49,
0x3d6dbcc4,0x3b49bd80,0xbd62bcf1,0xbd4e3d18,0x3c483d7b,0x3d783c79,0x3d22bd46,0xbcdbbd67,0xbd353d35,0x3cac3d71,0x3d7f3bc9,0x3d04bd5c,0xbd0ebd55,0xbd7d3c16,0xbc953d75,0x3d3e3d2c,
0xbd7b3c48,0xbcdb3d67,0x3cf13d62,0x3d7d3c16,0x3d6d3cc4,0x3d5cbd04,0x3bc9bd7f,0xbd3ebd2c,0xbd0ebd55,0xbd80bb49,0xbd223d46,0x3c793d78,0x3d80,0x3d4e3d18,0x3d75bc95,0x3cacbd71,
0x3d553d0e,0x3d71bcac,0x3c95bd75,0xbd18bd4e,0xbcc4bd6d,0xbd78bc79,0xbd463d22,0x3b493d80,0xbc483d7b,0x3d2c3d3e,0x3d7fbbc9,0x3d04bd5c,0x3d35bd35,0xbc16bd7d,0xbd62bcf1,0xbd673cdb,
0xbd353d35,0xbb493d80,0x3d223d46,0x3d7d3c16,0x3d55bd0e,0x3c79bd78,0xbcf1bd62,0xbd71bcac,0xbd6d3cc4,0xbcdb3d67,0x3c953d75,0x3d5c3d04,0x3d7bbc48,0x3d18bd4e,0xbbc9bd7f,0xbd3ebd2c,
0x3d80,0x3d2c3d3e,0x3d7f3bc9,0x3d4ebd18,0x3c48bd7b,0xbd04bd5c,0xbd75bc95,0xbd673cdb,0xbcc43d6d,0x3cac3d71,0x3d623cf1,0x3d78bc79,0x3d0ebd55,0xbc16bd7d,0xbd46bd22,0xbd803b49,
0xbd7bbc48,0xbd713cac,0xbd223d46,0xbc163d7d,0x3d35bd35,0x3c79bd78,0xbc95bd75,0xbd3ebd2c,0x3d0ebd55,0x3b49bd80,0xbcf1bd62,0xbd5cbd04,0x3cc43d6d,0x3d4e3d18,0x3d7f3bc9,0x3d67bcdb,
0x3d55bd0e,0x3cdbbd67,0xbbc9bd7f,0xbd18bd4e,0x3d80,0x3d043d5c,0x3d623cf1,0x3d80bb49,0x3c483d7b,0x3d2c3d3e,0x3d753c95,0x3d78bc79,0xbd6dbcc4,0xbd7d3c16,0xbd463d22,0xbcac3d71,
0x3d6dbcc4,0x3d3ebd2c,0x3cf1bd62,0x3c16bd7d,0xbc48bd7b,0xbd04bd5c,0xbd46bd22,0xbd71bcac,0xbd353d35,0xbcdb3d67,0xbbc93d7f,0x3c793d78,0x3d0e3d55,0x3d4e3d18,0x3d753c95,0x3d80bb49,
0x3cc4bd6d,0x3b49bd80,0xbc95bd75,0xbd18bd4e,0xbd55bd0e,0xbd78bc79,0xbd7f3bc9,0xbd673cdb,0x3d80,0x3cac3d71,0x3d223d46,0x3d5c3d04,0x3d7b3c48,0x3d7dbc16,0x3d62bcf1,0x3d2cbd3e,
0xbd55bd0e,0xbd67bcdb,0xbd75bc95,0xbd7dbc16,0xbcc4bd6d,0xbd04bd5c,0xbd22bd46,0xbd3ebd2c,0x3c48bd7b,0x3b49bd80,0xbbc9bd7f,0xbc79bd78,0x3d35bd35,0x3d18bd4e,0x3cf1bd62,0x3cacbd71,
0x3d7bbc48,0x3d71bcac,0x3d62bcf1,0x3d4ebd18,0x3d6d3cc4,0x3d783c79,0x3d7f3bc9,0x3d80bb49,0x3d0e3d55,0x3d2c3d3e,0x3d463d22,0x3d5c3d04,0x3d80,0x3c163d7d,0x3c953d75,0x3cdb3d67,
0xbd800000,0xbb493d80,0x3d7f3bc9,0x3c16bd7d,0xbd7bbc48,0xbc793d78,0x3d753c95,0x3cacbd71,0xbd6dbcc4,0xbcdb3d67,0x3d623cf1,0x3d04bd5c,0xbd55bd0e,0xbd183d4e,0x3d463d22,0x3d2cbd3e,
0xbd35bd35,0xbd3e3d2c,0x3d223d46,0x3d4ebd18,0xbd0ebd55,0xbd5c3d04,0x3cf13d62,0x3d67bcdb,0xbcc4bd6d,0xbd713cac,0x3c953d75,0x3d78bc79,0xbc48bd7b,0xbd7d3c16,0x3bc93d7f,0x3d80bb49,
0xbd0ebd55,0xbd713cac,0x3bc93d7f,0x3d7d3c16,0xbd800000,0xbc793d78,0x3d623cf1,0x3d2cbd3e,0x3d7bbc48,0x3b49bd80,0xbd75bc95,0xbd043d5c,0x3cc4bd6d,0xbd4ebd18,0xbd463d22,0x3cdb3d67,
0xbc483d7b,0x3d673cdb,0x3d22bd46,0xbd18bd4e,0x3d353d35,0x3d5cbd04,0xbc95bd75,0xbd803b49,0xbd55bd0e,0xbd3e3d2c,0x3cf13d62,0x3d78bc79,0xbd6d3cc4,0x3c163d7d,0x3d7f3bc9,0x3cacbd71,
0x3d6d3cc4,0x3d3ebd2c,0xbc95bd75,0xbd7dbc16,0xbd0e3d55,0x3d043d5c,0x3d7fbbc9,0x3cacbd71,0xbd800000,0xbcdb3d67,0x3d223d46,0x3d78bc79,0x3c48bd7b,0xbd4ebd18,0xbd623cf1,0x3b493d80,
0x3cc43d6d,0x3d803b49,0x3cf1bd62,0xbd18bd4e,0xbd7b3c48,0xbc793d78,0x3d463d22,0x3d67bcdb,0xbd35bd35,0xbd713cac,0xbbc93d7f,0x3d5c3d04,0x3d55bd0e,0xbc16bd7d,0xbd75bc95,0xbd2c3d3e,
0xbc48bd7b,0xbd67bcdb,0xbd623cf1,0xbc163d7d,0xbcc43d6d,0x3d043d5c,0x3d7f3bc9,0x3d2cbd3e,0x3d55bd0e,0x3b49bd80,0xbd46bd22,0xbd783c79,0xbd800000,0xbd183d4e,0x3c953d75,0x3d713cac,
0xbd0e3d55,0x3cac3d71,0x3d753c95,0x3d4ebd18,0x3d6dbcc4,0x3c79bd78,0xbd22bd46,0xbd803b49,0xbd7bbc48,0xbd3e3d2c,0x3bc93d7f,0x3d5c3d04,0x3d353d35,0x3d7dbc16,0x3cf1bd62,0xbcdbbd67,
0xbd35bd35,0xbd80bb49,0xbd463d22,0xbc163d7d,0x3d0e3d55,0x3d783c79,0x3d62bcf1,0x3cacbd71,0xbcc4bd6d,0xbd67bcdb,0xbd753c95,0xbd043d5c,0x3c483d7b,0x3d4e3d18,0x3d7fbbc9,0x3d2cbd3e,
0xbd800000,0xbd3e3d2c,0xbbc93d7f,0x3d183d4e,0x3d7b3c48,0x3d5cbd04,0x3c95bd75,0xbcdbbd67,0xbd6dbcc4,0xbd713cac,0xbcf13d62,0x3c793d78,0x3d553d0e,0x3d7dbc16,0x3d22bd46,0xbb49bd80,
0x3c48bd7b,0xbcacbd71,0xbd46bd22,0xbd7dbc16,0x3d353d35,0x3d783c79,0x3d75bc95,0x3d2cbd3e,0x3d553d0e,0x3d803b49,0x3d62bcf1,0x3d04bd5c,0xbd6d3cc4,0xbd183d4e,0xbbc93d7f,0x3cdb3d67,
0x3d0e3d55,0x3d673cdb,0x3d7fbbc9,0x3d4ebd18,0xbd800000,0xbd5c3d04,0xbcf13d62,0x3b493d80,0xbd7b3c48,0xbd3e3d2c,0xbc953d75,0x3c793d78,0x3cc4bd6d,0xbc16bd7d,0xbd22bd46,0xbd71bcac,
0x3cc43d6d,0x3d2c3d3e,0x3d623cf1,0x3d7d3c16,0x3d7bbc48,0x3d5cbd04,0x3d22bd46,0x3cacbd71,0xbd35bd35,0xbd67bcdb,0xbd7fbbc9,0xbd783c79,0xbd553d0e,0xbd183d4e,0xbc953d75,0x3b493d80,
0x3d6d3cc4,0x3d803b49,0x3d75bc95,0x3d4ebd18,0x3d0ebd55,0x3c79bd78,0xbbc9bd7f,0xbcdbbd67,0xbd800000,0xbd713cac,0xbd463d22,0xbd043d5c,0xbc483d7b,0x3c163d7d,0x3cf13d62,0x3d3e3d2c,
0x3d0ebd55,0x3cdbbd67,0x3c95bd75,0x3c16bd7d,0x3d6dbcc4,0x3d5cbd04,0x3d46bd22,0x3d2cbd3e,0x3d7b3c48,0x3d803b49,0x3d7fbbc9,0x3d78bc79,0x3d353d35,0x3d4e3d18,0x3d623cf1,0x3d713cac,
0x3c483d7b,0x3cac3d71,0x3cf13d62,0x3d183d4e,0xbcc43d6d,0xbc793d78,0xbbc93d7f,0x3b493d80,0xbd553d0e,0xbd3e3d2c,0xbd223d46,0xbd043d5c,0xbd800000,0xbd7d3c16,0xbd753c95,0xbd673cdb,
0x3d80,0xbbc93d7f,0xbc483d7b,0xbc953d75,0xbcc43d6d,0xbcf13d62,0xbd0e3d55,0xbd223d46,0xbd353d35,0xbd463d22,0xbd553d0e,0xbd623cf1,0xbd6d3cc4,0xbd753c95,0xbd7b3c48,0xbd7f3bc9,
0xbd800000,0xbd7fbbc9,0xbd7bbc48,0xbd75bc95,0xbd6dbcc4,0xbd62bcf1,0xbd55bd0e,0xbd46bd22,0xbd35bd35,0xbd22bd46,0xbd0ebd55,0xbcf1bd62,0xbcc4bd6d,0xbc95bd75,0xbc48bd7b,0xbbc9bd7f,
0xbd6d3cc4,0xbd7f3bc9,0xbd7bbc48,0xbd62bcf1,0x3d80,0xbc953d75,0xbd0e3d55,0xbd463d22,0x3cc4bd6d,0x3d22bd46,0x3d55bd0e,0x3d75bc95,0xbd35bd35,0xbcf1bd62,0xbc48bd7b,0x3bc9bd7f,
0x3cc43d6d,0x3bc93d7f,0xbc483d7b,0xbcf13d62,0x3d800000,0x3d753c95,0x3d553d0e,0x3d223d46,0xbd6dbcc4,0xbd46bd22,0xbd0ebd55,0xbc95bd75,0xbd353d35,0xbd623cf1,0xbd7b3c48,0xbd7fbbc9,
0x3d35bd35,0x3d75bc95,0x3d7b3c48,0x3d463d22,0x3cc43d6d,0xbbc93d7f,0xbd0e3d55,0xbd623cf1,0x3d80,0xbcf13d62,0xbd553d0e,0xbd7f3bc9,0xbd6dbcc4,0xbd22bd46,0xbc48bd7b,0x3c95bd75,
0x3d353d35,0x3c953d75,0xbc483d7b,0xbd223d46,0xbd6d3cc4,0xbd7fbbc9,0xbd55bd0e,0xbcf1bd62,0xbd800000,0xbd62bcf1,0xbd0ebd55,0xbbc9bd7f,0x3cc4bd6d,0x3d46bd22,0x3d7bbc48,0x3d753c95,
0xbd6dbcc4,0xbcf1bd62,0x3c48bd7b,0x3d46bd22,0x3d353d35,0x3bc93d7f,0xbd0e3d55,0xbd753c95,0xbcc4bd6d,0x3c95bd75,0x3d55bd0e,0x3d7f3bc9,0x3d80,0xbd223d46,0xbd7b3c48,0xbd62bcf1,
0xbcc43d6d,0xbd623cf1,0xbd7bbc48,0xbd22bd46,0x3d35bd35,0x3d7fbbc9,0x3d553d0e,0x3c953d75,0xbd6d3cc4,0xbd75bc95,0xbd0ebd55,0x3bc9bd7f,0x3d800000,0x3d463d22,0x3c483d7b,0xbcf13d62,
0xbd800000,0xbd22bd46,0x3c48bd7b,0x3d62bcf1,0x3d6d3cc4,0x3c953d75,0xbd0e3d55,0xbd7f3bc9,0xbd35bd35,0x3bc9bd7f,0x3d55bd0e,0x3d753c95,0x3cc43d6d,0xbcf13d62,0xbd7b3c48,0xbd46bd22,
0x3d80,0xbd463d22,0xbd7bbc48,0xbcf1bd62,0x3cc4bd6d,0x3d75bc95,0x3d553d0e,0x3bc93d7f,0xbd353d35,0xbd7fbbc9,0xbd0ebd55,0x3c95bd75,0x3d6dbcc4,0x3d623cf1,0x3c483d7b,0xbd223d46,
0xbcc4bd6d,0x3d22bd46,0x3d7b3c48,0x3c953d75,0x3d800000,0x3cf13d62,0xbd0e3d55,0xbd7fbbc9,0x3d6d3cc4,0x3bc93d7f,0xbd553d0e,0xbd62bcf1,0xbd353d35,0xbd75bc95,0xbc48bd7b,0x3d46bd22,
0x3d6dbcc4,0x3d463d22,0xbc483d7b,0xbd753c95,0x3d80,0xbd623cf1,0xbd55bd0e,0x3bc9bd7f,0xbcc43d6d,0xbd7f3bc9,0xbd0ebd55,0x3cf1bd62,0xbd35bd35,0x3c95bd75,0x3d7bbc48,0x3d223d46,
0x3d353d35,0xbcf13d62,0xbd7bbc48,0xbbc9bd7f,0x3d6dbcc4,0x3d223d46,0xbd0e3d55,0xbd75bc95,0xbd800000,0xbc95bd75,0x3d55bd0e,0x3d463d22,0xbcc43d6d,0xbd7fbbc9,0xbc48bd7b,0x3d62bcf1,
0x3d35bd35,0x3d623cf1,0xbc483d7b,0xbd7f3bc9,0xbcc4bd6d,0x3d46bd22,0x3d553d0e,0xbc953d75,0x3d80,0xbd753c95,0xbd0ebd55,0x3d22bd46,0x3d6d3cc4,0xbbc93d7f,0xbd7b3c48,0xbcf1bd62,
0x3cc4bd6d,0x3d753c95,0xbc483d7b,0xbd7fbbc9,0x3d35bd35,0x3d463d22,0xbd0e3d55,0xbd62bcf1,0x3d6dbcc4,0x3cf13d62,0xbd553d0e,0xbd22bd46,0x3d800000,0x3bc93d7f,0xbd7b3c48,0xbc95bd75,
0x3d6d3cc4,0xbc953d75,0xbd7bbc48,0x3bc9bd7f,0x3d353d35,0xbd223d46,0xbd55bd0e,0x3cf1bd62,0x3cc43d6d,0xbd623cf1,0xbd0ebd55,0x3d46bd22,0x3d80,0xbd7f3bc9,0xbc48bd7b,0x3d75bc95,
0xbd800000,0xbd7fbbc9,0xbd7bbc48,0xbd75bc95,0xbd6dbcc4,0xbd62bcf1,0xbd55bd0e,0xbd46bd22,0xbd35bd35,0xbd22bd46,0xbd0ebd55,0xbcf1bd62,0xbcc4bd6d,0xbc95bd75,0xbc48bd7b,0xbbc9bd7f,
0x8000bd80,0x3bc9bd7f,0x3c48bd7b,0x3c95bd75,0x3cc4bd6d,0x3cf1bd62,0x3d0ebd55,0x3d22bd46,0x3d35bd35,0x3d46bd22,0x3d55bd0e,0x3d62bcf1,0x3d6dbcc4,0x3d75bc95,0x3d7bbc48,0x3d7fbbc9,
0xbcc4bd6d,0xbbc9bd7f,0x3c48bd7b,0x3cf1bd62,0xbd800000,0xbd75bc95,0xbd55bd0e,0xbd22bd46,0x3d6d3cc4,0x3d463d22,0x3d0e3d55,0x3c953d75,0x3d35bd35,0x3d62bcf1,0x3d7bbc48,0x3d7f3bc9,
0xbd6d3cc4,0xbd7f3bc9,0xbd7bbc48,0xbd62bcf1,0x80003d80,0xbc953d75,0xbd0e3d55,0xbd463d22,0x3cc4bd6d,0x3d22bd46,0x3d55bd0e,0x3d75bc95,0xbd35bd35,0xbcf1bd62,0xbc48bd7b,0x3bc9bd7f,
0x3d353d35,0x3c953d75,0xbc483d7b,0xbd223d46,0xbd6d3cc4,0xbd7fbbc9,0xbd55bd0e,0xbcf1bd62,0xbd800000,0xbd62bcf1,0xbd0ebd55,0xbbc9bd7f,0x3cc4bd6d,0x3d46bd22,0x3d7bbc48,0x3d753c95,
0xbd353d35,0xbd753c95,0xbd7bbc48,0xbd46bd22,0xbcc4bd6d,0x3bc9bd7f,0x3d0ebd55,0x3d62bcf1,0x8000bd80,0x3cf1bd62,0x3d55bd0e,0x3d7fbbc9,0x3d6d3cc4,0x3d223d46,0x3c483d7b,0xbc953d75,
0x3cc4bd6d,0x3d62bcf1,0x3d7b3c48,0x3d223d46,0xbd353d35,0xbd7f3bc9,0xbd55bd0e,0xbc95bd75,0x3d6dbcc4,0x3d753c95,0x3d0e3d55,0xbbc93d7f,0xbd800000,0xbd46bd22,0xbc48bd7b,0x3cf1bd62,
0xbd6dbcc4,0xbcf1bd62,0x3c48bd7b,0x3d46bd22,0x3d353d35,0x3bc93d7f,0xbd0e3d55,0xbd753c95,0xbcc4bd6d,0x3c95bd75,0x3d55bd0e,0x3d7f3bc9,0x80003d80,0xbd223d46,0xbd7b3c48,0xbd62bcf1,
0x8000bd80,0x3d46bd22,0x3d7b3c48,0x3cf13d62,0xbcc43d6d,0xbd753c95,0xbd55bd0e,0xbbc9bd7f,0x3d35bd35,0x3d7f3bc9,0x3d0e3d55,0xbc953d75,0xbd6d3cc4,0xbd62bcf1,0xbc48bd7b,0x3d22bd46,
0xbd800000,0xbd22bd46,0x3c48bd7b,0x3d62bcf1,0x3d6d3cc4,0x3c953d75,0xbd0e3d55,0xbd7f3bc9,0xbd35bd35,0x3bc9bd7f,0x3d55bd0e,0x3d753c95,0x3cc43d6d,0xbcf13d62,0xbd7b3c48,0xbd46bd22,
0x3d6dbcc4,0x3d463d22,0xbc483d7b,0xbd753c95,0x80003d80,0xbd623cf1,0xbd55bd0e,0x3bc9bd7f,0xbcc43d6d,0xbd7f3bc9,0xbd0ebd55,0x3cf1bd62,0xbd35bd35,0x3c95bd75,0x3d7bbc48,0x3d223d46,
0x3cc43d6d,0xbd223d46,0xbd7bbc48,0xbc95bd75,0xbd800000,0xbcf1bd62,0x3d0ebd55,0x3d7f3bc9,0xbd6dbcc4,0xbbc9bd7f,0x3d55bd0e,0x3d623cf1,0x3d35bd35,0x3d753c95,0x3c483d7b,0xbd463d22,
0xbd353d35,0xbd62bcf1,0x3c48bd7b,0x3d7fbbc9,0x3cc43d6d,0xbd463d22,0xbd55bd0e,0x3c95bd75,0x8000bd80,0x3d75bc95,0x3d0e3d55,0xbd223d46,0xbd6dbcc4,0x3bc9bd7f,0x3d7bbc48,0x3cf13d62,
0x3d353d35,0xbcf13d62,0xbd7bbc48,0xbbc9bd7f,0x3d6dbcc4,0x3d223d46,0xbd0e3d55,0xbd75bc95,0xbd800000,0xbc95bd75,0x3d55bd0e,0x3d463d22,0xbcc43d6d,0xbd7fbbc9,0xbc48bd7b,0x3d62bcf1,
0x3d6d3cc4,0xbc953d75,0xbd7bbc48,0x3bc9bd7f,0x3d353d35,0xbd223d46,0xbd55bd0e,0x3cf1bd62,0x3cc43d6d,0xbd623cf1,0xbd0ebd55,0x3d46bd22,0x80003d80,0xbd7f3bc9,0xbc48bd7b,0x3d75bc95,
0xbcc43d6d,0xbd75bc95,0x3c48bd7b,0x3d7f3bc9,0xbd353d35,0xbd46bd22,0x3d0ebd55,0x3d623cf1,0xbd6d3cc4,0xbcf1bd62,0x3d55bd0e,0x3d223d46,0xbd800000,0xbbc9bd7f,0x3d7bbc48,0x3c953d75,
0x3d80,0xbd7fbbc9,0x3c48bd7b,0x3d753c95,0xbcc43d6d,0xbd62bcf1,0x3d0ebd55,0x3d463d22,0xbd353d35,0xbd22bd46,0x3d55bd0e,0x3cf13d62,0xbd6d3cc4,0xbc95bd75,0x3d7bbc48,0x3bc93d7f,
0xbd800000,0x3bc9bd7f,0x3d7b3c48,0xbc953d75,0xbd6dbcc4,0x3cf1bd62,0x3d553d0e,0xbd223d46,0xbd35bd35,0x3d46bd22,0x3d0e3d55,0xbd623cf1,0xbcc4bd6d,0x3d75bc95,0x3c483d7b,0xbd7f3bc9,
0xbd6d3cc4,0xbbc9bd7f,0x3d7b3c48,0xbcf13d62,0x3d80,0xbd75bc95,0x3d0ebd55,0x3d223d46,0x3cc4bd6d,0x3d463d22,0xbd553d0e,0xbc95bd75,0xbd35bd35,0x3d62bcf1,0x3c483d7b,0xbd7fbbc9,
0x3cc43d6d,0xbd7f3bc9,0x3c48bd7b,0x3d623cf1,0x3d800000,0xbc953d75,0xbd55bd0e,0x3d46bd22,0xbd6dbcc4,0x3d22bd46,0x3d0e3d55,0xbd753c95,0xbd353d35,0xbcf1bd62,0x3d7bbc48,0xbbc93d7f,
0x3d35bd35,0x3c953d75,0xbd7bbc48,0x3d22bd46,0x3cc43d6d,0xbd7fbbc9,0x3d0ebd55,0x3cf13d62,0x3d80,0xbd62bcf1,0x3d55bd0e,0x3bc93d7f,0xbd6dbcc4,0x3d46bd22,0x3c483d7b,0xbd75bc95,
0x3d353d35,0xbd753c95,0x3c48bd7b,0x3d463d22,0xbd6d3cc4,0x3bc9bd7f,0x3d553d0e,0xbd623cf1,0xbd800000,0x3cf1bd62,0x3d0e3d55,0xbd7f3bc9,0x3cc4bd6d,0x3d223d46,0xbd7b3c48,0x3c95bd75,
0xbd6dbcc4,0x3d62bcf1,0xbc483d7b,0xbd22bd46,0x3d353d35,0xbd7f3bc9,0x3d0ebd55,0x3c953d75,0xbcc4bd6d,0x3d753c95,0xbd553d0e,0x3bc9bd7f,0x3d80,0xbd46bd22,0x3d7bbc48,0xbcf13d62,
0xbcc43d6d,0xbcf1bd62,0x3d7b3c48,0xbd463d22,0x3d35bd35,0x3bc93d7f,0xbd55bd0e,0x3d75bc95,0xbd6d3cc4,0x3c95bd75,0x3d0e3d55,0xbd7fbbc9,0x3d800000,0xbd223d46,0xbc48bd7b,0x3d623cf1,
0xbd800000,0x3d46bd22,0xbc483d7b,0xbcf1bd62,0x3d6d3cc4,0xbd753c95,0x3d0ebd55,0x3bc93d7f,0xbd35bd35,0x3d7f3bc9,0xbd553d0e,0x3c95bd75,0x3cc43d6d,0xbd62bcf1,0x3d7bbc48,0xbd223d46,
0x3d80,0xbd22bd46,0x3d7b3c48,0xbd623cf1,0x3cc4bd6d,0x3c953d75,0xbd55bd0e,0x3d7fbbc9,0xbd353d35,0x3bc9bd7f,0x3d0e3d55,0xbd75bc95,0x3d6dbcc4,0xbcf13d62,0xbc48bd7b,0x3d463d22,
0xbcc4bd6d,0x3d463d22,0xbd7bbc48,0x3d75bc95,0x3d800000,0xbd623cf1,0x3d0ebd55,0xbbc93d7f,0x3d6d3cc4,0xbd7f3bc9,0x3d55bd0e,0xbcf13d62,0xbd353d35,0x3c95bd75,0x3c483d7b,0xbd22bd46,
0x3d6dbcc4,0xbd223d46,0x3c48bd7b,0x3c953d75,0x3d80,0xbcf1bd62,0x3d553d0e,0xbd7fbbc9,0xbcc43d6d,0xbbc9bd7f,0x3d0e3d55,0xbd62bcf1,0xbd35bd35,0x3d753c95,0xbd7b3c48,0x3d46bd22,
0x3d353d35,0xbd62bcf1,0x3d7b3c48,0xbd7f3bc9,0x3d6dbcc4,0xbd463d22,0x3d0ebd55,0xbc953d75,0xbd800000,0x3d75bc95,0xbd553d0e,0x3d22bd46,0xbcc43d6d,0x3bc9bd7f,0x3c483d7b,0xbcf1bd62,
0x3d35bd35,0xbcf13d62,0x3c48bd7b,0x3bc93d7f,0xbcc4bd6d,0x3d223d46,0xbd55bd0e,0x3d753c95,0x3d80,0xbc95bd75,0x3d0e3d55,0xbd46bd22,0x3d6d3cc4,0xbd7fbbc9,0x3d7bbc48,0xbd623cf1,
0x3cc4bd6d,0xbc953d75,0x3c48bd7b,0xbbc93d7f,0x3d35bd35,0xbd223d46,0x3d0ebd55,0xbcf13d62,0x3d6dbcc4,0xbd623cf1,0x3d55bd0e,0xbd463d22,0x3d800000,0xbd7f3bc9,0x3d7bbc48,0xbd753c95,
0x3d6d3cc4,0xbd75bc95,0x3d7b3c48,0xbd7fbbc9,0x3d353d35,0xbd46bd22,0x3d553d0e,0xbd62bcf1,0x3cc43d6d,0xbcf1bd62,0x3d0e3d55,0xbd22bd46,0x3d80,0xbbc9bd7f,0x3c483d7b,0xbc95bd75,
0xbd800000,0x3bc9bd7f,0x3d7b3c48,0xbc953d75,0xbd6dbcc4,0x3cf1bd62,0x3d553d0e,0xbd223d46,0xbd35bd35,0x3d46bd22,0x3d0e3d55,0xbd623cf1,0xbcc4bd6d,0x3d75bc95,0x3c483d7b,0xbd7f3bc9,
0x8000bd80,0x3d7f3bc9,0xbc483d7b,0xbd75bc95,0x3cc4bd6d,0x3d623cf1,0xbd0e3d55,0xbd46bd22,0x3d35bd35,0x3d223d46,0xbd553d0e,0xbcf1bd62,0x3d6dbcc4,0x3c953d75,0xbd7b3c48,0xbbc9bd7f,
0xbcc4bd6d,0x3d7fbbc9,0xbc483d7b,0xbd62bcf1,0xbd800000,0x3c95bd75,0x3d553d0e,0xbd463d22,0x3d6d3cc4,0xbd223d46,0xbd0ebd55,0x3d75bc95,0x3d35bd35,0x3cf13d62,0xbd7b3c48,0x3bc9bd7f,
0xbd6d3cc4,0xbbc9bd7f,0x3d7b3c48,0xbcf13d62,0x80003d80,0xbd75bc95,0x3d0ebd55,0x3d223d46,0x3cc4bd6d,0x3d463d22,0xbd553d0e,0xbc95bd75,0xbd35bd35,0x3d62bcf1,0x3c483d7b,0xbd7fbbc9,
0x3d353d35,0xbd753c95,0x3c48bd7b,0x3d463d22,0xbd6d3cc4,0x3bc9bd7f,0x3d553d0e,0xbd623cf1,0xbd800000,0x3cf1bd62,0x3d0e3d55,0xbd7f3bc9,0x3cc4bd6d,0x3d223d46,0xbd7b3c48,0x3c95bd75,
0xbd353d35,0xbc95bd75,0x3d7b3c48,0xbd223d46,0xbcc4bd6d,0x3d7f3bc9,0xbd0e3d55,0xbcf1bd62,0x8000bd80,0x3d623cf1,0xbd553d0e,0xbbc9bd7f,0x3d6d3cc4,0xbd463d22,0xbc48bd7b,0x3d753c95,
0x3cc4bd6d,0x3cf13d62,0xbd7bbc48,0x3d46bd22,0xbd353d35,0xbbc9bd7f,0x3d553d0e,0xbd753c95,0x3d6dbcc4,0xbc953d75,0xbd0ebd55,0x3d7f3bc9,0xbd800000,0x3d22bd46,0x3c483d7b,0xbd62bcf1,
0xbd6dbcc4,0x3d62bcf1,0xbc483d7b,0xbd22bd46,0x3d353d35,0xbd7f3bc9,0x3d0ebd55,0x3c953d75,0xbcc4bd6d,0x3d753c95,0xbd553d0e,0x3bc9bd7f,0x80003d80,0xbd46bd22,0x3d7bbc48,0xbcf13d62,
0x8000bd80,0x3d223d46,0xbd7bbc48,0x3d62bcf1,0xbcc43d6d,0xbc95bd75,0x3d553d0e,0xbd7f3bc9,0x3d35bd35,0xbbc93d7f,0xbd0ebd55,0x3d753c95,0xbd6d3cc4,0x3cf1bd62,0x3c483d7b,0xbd46bd22,
0xbd800000,0x3d46bd22,0xbc483d7b,0xbcf1bd62,0x3d6d3cc4,0xbd753c95,0x3d0ebd55,0x3bc93d7f,0xbd35bd35,0x3d7f3bc9,0xbd553d0e,0x3c95bd75,0x3cc43d6d,0xbd62bcf1,0x3d7bbc48,0xbd223d46,
0x3d6dbcc4,0xbd223d46,0x3c48bd7b,0x3c953d75,0x80003d80,0xbcf1bd62,0x3d553d0e,0xbd7fbbc9,0xbcc43d6d,0xbbc9bd7f,0x3d0e3d55,0xbd62bcf1,0xbd35bd35,0x3d753c95,0xbd7b3c48,0x3d46bd22,
0x3cc43d6d,0xbd46bd22,0x3d7b3c48,0xbd753c95,0xbd800000,0x3d62bcf1,0xbd0e3d55,0x3bc9bd7f,0xbd6dbcc4,0x3d7fbbc9,0xbd553d0e,0x3cf1bd62,0x3d35bd35,0xbc953d75,0xbc48bd7b,0x3d223d46,
0xbd353d35,0x3cf1bd62,0xbc483d7b,0xbbc9bd7f,0x3cc43d6d,0xbd22bd46,0x3d553d0e,0xbd75bc95,0x8000bd80,0x3c953d75,0xbd0ebd55,0x3d463d22,0xbd6dbcc4,0x3d7f3bc9,0xbd7b3c48,0x3d62bcf1,
0x3d353d35,0xbd62bcf1,0x3d7b3c48,0xbd7f3bc9,0x3d6dbcc4,0xbd463d22,0x3d0ebd55,0xbc953d75,0xbd800000,0x3d75bc95,0xbd553d0e,0x3d22bd46,0xbcc43d6d,0x3bc9bd7f,0x3c483d7b,0xbcf1bd62,
0x3d6d3cc4,0xbd75bc95,0x3d7b3c48,0xbd7fbbc9,0x3d353d35,0xbd46bd22,0x3d553d0e,0xbd62bcf1,0x3cc43d6d,0xbcf1bd62,0x3d0e3d55,0xbd22bd46,0x80003d80,0xbbc9bd7f,0x3c483d7b,0xbc95bd75,
0xbcc43d6d,0x3c95bd75,0xbc483d7b,0x3bc9bd7f,0xbd353d35,0x3d22bd46,0xbd0e3d55,0x3cf1bd62,0xbd6d3cc4,0x3d62bcf1,0xbd553d0e,0x3d46bd22,0xbd800000,0x3d7fbbc9,0xbd7b3c48,0x3d75bc95,
0x3d80,0x3bc9bd7f,0xbc483d7b,0x3c95bd75,0xbcc43d6d,0x3cf1bd62,0xbd0e3d55,0x3d22bd46,0xbd353d35,0x3d46bd22,0xbd553d0e,0x3d62bcf1,0xbd6d3cc4,0x3d75bc95,0xbd7b3c48,0x3d7fbbc9,
0xbd800000,0x3d7f3bc9,0xbd7bbc48,0x3d753c95,0xbd6dbcc4,0x3d623cf1,0xbd55bd0e,0x3d463d22,0xbd35bd35,0x3d223d46,0xbd0ebd55,0x3cf13d62,0xbcc4bd6d,0x3c953d75,0xbc48bd7b,0x3bc93d7f,
0xbd6d3cc4,0x3d7fbbc9,0xbd7bbc48,0x3d623cf1,0x3d80,0x3c95bd75,0xbd0e3d55,0x3d46bd22,0x3cc4bd6d,0xbd223d46,0x3d55bd0e,0xbd753c95,0xbd35bd35,0x3cf13d62,0xbc48bd7b,0xbbc93d7f,
0x3cc43d6d,0xbbc9bd7f,0xbc483d7b,0x3cf1bd62,0x3d800000,0xbd75bc95,0x3d553d0e,0xbd22bd46,0xbd6dbcc4,0x3d463d22,0xbd0ebd55,0x3c953d75,0xbd353d35,0x3d62bcf1,0xbd7b3c48,0x3d7f3bc9,
0x3d35bd35,0xbd753c95,0x3d7b3c48,0xbd46bd22,0x3cc43d6d,0x3bc9bd7f,0xbd0e3d55,0x3d62bcf1,0x3d80,0x3cf1bd62,0xbd553d0e,0x3d7fbbc9,0xbd6dbcc4,0x3d223d46,0xbc48bd7b,0xbc953d75,
0x3d353d35,0xbc95bd75,0xbc483d7b,0x3d22bd46,0xbd6d3cc4,0x3d7f3bc9,0xbd55bd0e,0x3cf13d62,0xbd800000,0x3d623cf1,0xbd0ebd55,0x3bc93d7f,0x3cc4bd6d,0xbd463d22,0x3d7bbc48,0xbd75bc95,
0xbd6dbcc4,0x3cf13d62,0x3c48bd7b,0xbd463d22,0x3d353d35,0xbbc9bd7f,0xbd0e3d55,0x3d75bc95,0xbcc4bd6d,0xbc953d75,0x3d55bd0e,0xbd7fbbc9,0x3d80,0x3d22bd46,0xbd7b3c48,0x3d623cf1,
0xbcc43d6d,0x3d62bcf1,0xbd7bbc48,0x3d223d46,0x3d35bd35,0xbd7f3bc9,0x3d553d0e,0xbc95bd75,0xbd6d3cc4,0x3d753c95,0xbd0ebd55,0xbbc93d7f,0x3d800000,0xbd46bd22,0x3c483d7b,0x3cf1bd62,
0xbd800000,0x3d223d46,0x3c48bd7b,0xbd623cf1,0x3d6d3cc4,0xbc95bd75,0xbd0e3d55,0x3d7fbbc9,0xbd35bd35,0xbbc93d7f,0x3d55bd0e,0xbd75bc95,0x3cc43d6d,0x3cf1bd62,0xbd7b3c48,0x3d463d22,
0x3d80,0x3d46bd22,0xbd7bbc48,0x3cf13d62,0x3cc4bd6d,0xbd753c95,0x3d553d0e,0xbbc9bd7f,0xbd353d35,0x3d7f3bc9,0xbd0ebd55,0xbc953d75,0x3d6dbcc4,0xbd62bcf1,0x3c483d7b,0x3d22bd46,
0xbcc4bd6d,0xbd223d46,0x3d7b3c48,0xbc95bd75,0x3d800000,0xbcf1bd62,0xbd0e3d55,0x3d7f3bc9,0x3d6d3cc4,0xbbc9bd7f,0xbd553d0e,0x3d623cf1,0xbd353d35,0x3d753c95,0xbc48bd7b,0xbd463d22,
0x3d6dbcc4,0xbd46bd22,0xbc483d7b,0x3d75bc95,0x3d80,0x3d62bcf1,0xbd55bd0e,0xbbc93d7f,0xbcc43d6d,0x3d7fbbc9,0xbd0ebd55,0xbcf13d62,0xbd35bd35,0xbc953d75,0x3d7bbc48,0xbd22bd46,
0x3d353d35,0x3cf1bd62,0xbd7bbc48,0x3bc93d7f,0x3d6dbcc4,0xbd22bd46,0xbd0e3d55,0x3d753c95,0xbd800000,0x3c953d75,0x3d55bd0e,0xbd46bd22,0xbcc43d6d,0x3d7f3bc9,0xbc48bd7b,0xbd623cf1,
0x3d35bd35,0xbd62bcf1,0xbc483d7b,0x3d7fbbc9,0xbcc4bd6d,0xbd463d22,0x3d553d0e,0x3c95bd75,0x3d80,0x3d75bc95,0xbd0ebd55,0xbd223d46,0x3d6d3cc4,0x3bc9bd7f,0xbd7b3c48,0x3cf13d62,
0x3cc4bd6d,0xbd75bc95,0xbc483d7b,0x3d7f3bc9,0x3d35bd35,0xbd46bd22,0xbd0e3d55,0x3d623cf1,0x3d6dbcc4,0xbcf1bd62,0xbd553d0e,0x3d223d46,0x3d800000,0xbbc9bd7f,0xbd7b3c48,0x3c953d75,
0x3d6d3cc4,0x3c95bd75,0xbd7bbc48,0xbbc93d7f,0x3d353d35,0x3d22bd46,0xbd55bd0e,0xbcf13d62,0x3cc43d6d,0x3d62bcf1,0xbd0ebd55,0xbd463d22,0x3d80,0x3d7fbbc9,0xbc48bd7b,0xbd753c95,
0xbd800000,0x3d7f3bc9,0xbd7bbc48,0x3d753c95,0xbd6dbcc4,0x3d623cf1,0xbd55bd0e,0x3d463d22,0xbd35bd35,0x3d223d46,0xbd0ebd55,0x3cf13d62,0xbcc4bd6d,0x3c953d75,0xbc48bd7b,0x3bc93d7f,
0x8000bd80,0xbbc93d7f,0x3c48bd7b,0xbc953d75,0x3cc4bd6d,0xbcf13d62,0x3d0ebd55,0xbd223d46,0x3d35bd35,0xbd463d22,0x3d55bd0e,0xbd623cf1,0x3d6dbcc4,0xbd753c95,0x3d7bbc48,0xbd7f3bc9,
0xbcc4bd6d,0x3bc93d7f,0x3c48bd7b,0xbcf13d62,0xbd800000,0x3d753c95,0xbd55bd0e,0x3d223d46,0x3d6d3cc4,0xbd46bd22,0x3d0e3d55,0xbc95bd75,0x3d35bd35,0xbd623cf1,0x3d7bbc48,0xbd7fbbc9,
0xbd6d3cc4,0x3d7fbbc9,0xbd7bbc48,0x3d623cf1,0x80003d80,0x3c95bd75,0xbd0e3d55,0x3d46bd22,0x3cc4bd6d,0xbd223d46,0x3d55bd0e,0xbd753c95,0xbd35bd35,0x3cf13d62,0xbc48bd7b,0xbbc93d7f,
0x3d353d35,0xbc95bd75,0xbc483d7b,0x3d22bd46,0xbd6d3cc4,0x3d7f3bc9,0xbd55bd0e,0x3cf13d62,0xbd800000,0x3d623cf1,0xbd0ebd55,0x3bc93d7f,0x3cc4bd6d,0xbd463d22,0x3d7bbc48,0xbd75bc95,
0xbd353d35,0x3d75bc95,0xbd7bbc48,0x3d463d22,0xbcc4bd6d,0xbbc93d7f,0x3d0ebd55,0xbd623cf1,0x8000bd80,0xbcf13d62,0x3d55bd0e,0xbd7f3bc9,0x3d6d3cc4,0xbd22bd46,0x3c483d7b,0x3c95bd75,
0x3cc4bd6d,0xbd623cf1,0x3d7b3c48,0xbd22bd46,0xbd353d35,0x3d7fbbc9,0xbd55bd0e,0x3c953d75,0x3d6dbcc4,0xbd75bc95,0x3d0e3d55,0x3bc9bd7f,0xbd800000,0x3d463d22,0xbc48bd7b,0xbcf13d62,
0xbd6dbcc4,0x3cf13d62,0x3c48bd7b,0xbd463d22,0x3d353d35,0xbbc9bd7f,0xbd0e3d55,0x3d75bc95,0xbcc4bd6d,0xbc953d75,0x3d55bd0e,0xbd7fbbc9,0x80003d80,0x3d22bd46,0xbd7b3c48,0x3d623cf1,
0x8000bd80,0xbd463d22,0x3d7b3c48,0xbcf1bd62,0xbcc43d6d,0x3d75bc95,0xbd55bd0e,0x3bc93d7f,0x3d35bd35,0xbd7fbbc9,0x3d0e3d55,0x3c95bd75,0xbd6d3cc4,0x3d623cf1,0xbc48bd7b,0xbd223d46,
0xbd800000,0x3d223d46,0x3c48bd7b,0xbd623cf1,0x3d6d3cc4,0xbc95bd75,0xbd0e3d55,0x3d7fbbc9,0xbd35bd35,0xbbc93d7f,0x3d55bd0e,0xbd75bc95,0x3cc43d6d,0x3cf1bd62,0xbd7b3c48,0x3d463d22,
0x3d6dbcc4,0xbd46bd22,0xbc483d7b,0x3d75bc95,0x80003d80,0x3d62bcf1,0xbd55bd0e,0xbbc93d7f,0xbcc43d6d,0x3d7fbbc9,0xbd0ebd55,0xbcf13d62,0xbd35bd35,0xbc953d75,0x3d7bbc48,0xbd22bd46,
0x3cc43d6d,0x3d22bd46,0xbd7bbc48,0x3c953d75,0xbd800000,0x3cf13d62,0x3d0ebd55,0xbd7fbbc9,0xbd6dbcc4,0x3bc93d7f,0x3d55bd0e,0xbd62bcf1,0x3d35bd35,0xbd75bc95,0x3c483d7b,0x3d46bd22,
0xbd353d35,0x3d623cf1,0x3c48bd7b,0xbd7f3bc9,0x3cc43d6d,0x3d46bd22,0xbd55bd0e,0xbc953d75,0x8000bd80,0xbd753c95,0x3d0e3d55,0x3d22bd46,0xbd6dbcc4,0xbbc93d7f,0x3d7bbc48,0xbcf1bd62,
0x3d353d35,0x3cf1bd62,0xbd7bbc48,0x3bc93d7f,0x3d6dbcc4,0xbd22bd46,0xbd0e3d55,0x3d753c95,0xbd800000,0x3c953d75,0x3d55bd0e,0xbd46bd22,0xbcc43d6d,0x3d7f3bc9,0xbc48bd7b,0xbd623cf1,
0x3d6d3cc4,0x3c95bd75,0xbd7bbc48,0xbbc93d7f,0x3d353d35,0x3d22bd46,0xbd55bd0e,0xbcf13d62,0x3cc43d6d,0x3d62bcf1,0xbd0ebd55,0xbd463d22,0x80003d80,0x3d7fbbc9,0xbc48bd7b,0xbd753c95,
0xbcc43d6d,0x3d753c95,0x3c48bd7b,0xbd7fbbc9,0xbd353d35,0x3d463d22,0x3d0ebd55,0xbd62bcf1,0xbd6d3cc4,0x3cf13d62,0x3d55bd0e,0xbd22bd46,0xbd800000,0x3bc93d7f,0x3d7bbc48,0xbc95bd75,
0x3d80,0x3d7f3bc9,0x3c48bd7b,0xbd75bc95,0xbcc43d6d,0x3d623cf1,0x3d0ebd55,0xbd46bd22,0xbd353d35,0x3d223d46,0x3d55bd0e,0xbcf1bd62,0xbd6d3cc4,0x3c953d75,0x3d7bbc48,0xbbc9bd7f,
0xbd800000,0xbbc93d7f,0x3d7b3c48,0x3c95bd75,0xbd6dbcc4,0xbcf13d62,0x3d553d0e,0x3d22bd46,0xbd35bd35,0xbd463d22,0x3d0e3d55,0x3d62bcf1,0xbcc4bd6d,0xbd753c95,0x3c483d7b,0x3d7fbbc9,
0xbd6d3cc4,0x3bc93d7f,0x3d7b3c48,0x3cf1bd62,0x3d80,0x3d753c95,0x3d0ebd55,0xbd22bd46,0x3cc4bd6d,0xbd46bd22,0xbd553d0e,0x3c953d75,0xbd35bd35,0xbd623cf1,0x3c483d7b,0x3d7f3bc9,
0x3cc43d6d,0x3d7fbbc9,0x3c48bd7b,0xbd62bcf1,0x3d800000,0x3c95bd75,0xbd55bd0e,0xbd463d22,0xbd6dbcc4,0xbd223d46,0x3d0e3d55,0x3d75bc95,0xbd353d35,0x3cf13d62,0x3d7bbc48,0x3bc9bd7f,
0x3d35bd35,0xbc95bd75,0xbd7bbc48,0xbd223d46,0x3cc43d6d,0x3d7f3bc9,0x3d0ebd55,0xbcf1bd62,0x3d80,0x3d623cf1,0x3d55bd0e,0xbbc9bd7f,0xbd6dbcc4,0xbd463d22,0x3c483d7b,0x3d753c95,
0x3d353d35,0x3d75bc95,0x3c48bd7b,0xbd46bd22,0xbd6d3cc4,0xbbc93d7f,0x3d553d0e,0x3d62bcf1,0xbd800000,0xbcf13d62,0x3d0e3d55,0x3d7fbbc9,0x3cc4bd6d,0xbd22bd46,0xbd7b3c48,0xbc953d75,
0xbd6dbcc4,0xbd623cf1,0xbc483d7b,0x3d223d46,0x3d353d35,0x3d7fbbc9,0x3d0ebd55,0xbc95bd75,0xbcc4bd6d,0xbd75bc95,0xbd553d0e,0xbbc93d7f,0x3d80,0x3d463d22,0x3d7bbc48,0x3cf1bd62,
0xbcc43d6d,0x3cf13d62,0x3d7b3c48,0x3d46bd22,0x3d35bd35,0xbbc9bd7f,0xbd55bd0e,0xbd753c95,0xbd6d3cc4,0xbc953d75,0x3d0e3d55,0x3d7f3bc9,0x3d800000,0x3d22bd46,0xbc48bd7b,0xbd62bcf1,
0xbd800000,0xbd463d22,0xbc483d7b,0x3cf13d62,0x3d6d3cc4,0x3d75bc95,0x3d0ebd55,0xbbc9bd7f,0xbd35bd35,0xbd7fbbc9,0xbd553d0e,0xbc953d75,0x3cc43d6d,0x3d623cf1,0x3d7bbc48,0x3d22bd46,
0x3d80,0x3d223d46,0x3d7b3c48,0x3d62bcf1,0x3cc4bd6d,0xbc95bd75,0xbd55bd0e,0xbd7f3bc9,0xbd353d35,0xbbc93d7f,0x3d0e3d55,0x3d753c95,0x3d6dbcc4,0x3cf1bd62,0xbc48bd7b,0xbd46bd22,
0xbcc4bd6d,0xbd46bd22,0xbd7bbc48,0xbd753c95,0x3d800000,0x3d62bcf1,0x3d0ebd55,0x3bc9bd7f,0x3d6d3cc4,0x3d7fbbc9,0x3d55bd0e,0x3cf1bd62,0xbd353d35,0xbc953d75,0x3c483d7b,0x3d223d46,
0x3d6dbcc4,0x3d22bd46,0x3c48bd7b,0xbc95bd75,0x3d80,0x3cf13d62,0x3d553d0e,0x3d7f3bc9,0xbcc43d6d,0x3bc93d7f,0x3d0e3d55,0x3d623cf1,0xbd35bd35,0xbd75bc95,0xbd7b3c48,0xbd463d22,
0x3d353d35,0x3d623cf1,0x3d7b3c48,0x3d7fbbc9,0x3d6dbcc4,0x3d46bd22,0x3d0ebd55,0x3c95bd75,0xbd800000,0xbd753c95,0xbd553d0e,0xbd223d46,0xbcc43d6d,0xbbc93d7f,0x3c483d7b,0x3cf13d62,
0x3d35bd35,0x3cf1bd62,0x3c48bd7b,0xbbc9bd7f,0xbcc4bd6d,0xbd22bd46,0xbd55bd0e,0xbd75bc95,0x3d80,0x3c953d75,0x3d0e3d55,0x3d463d22,0x3d6d3cc4,0x3d7f3bc9,0x3d7bbc48,0x3d62bcf1,
0x3cc4bd6d,0x3c95bd75,0x3c48bd7b,0x3bc9bd7f,0x3d35bd35,0x3d22bd46,0x3d0ebd55,0x3cf1bd62,0x3d6dbcc4,0x3d62bcf1,0x3d55bd0e,0x3d46bd22,0x3d800000,0x3d7fbbc9,0x3d7bbc48,0x3d75bc95,
0x3d6d3cc4,0x3d753c95,0x3d7b3c48,0x3d7f3bc9,0x3d353d35,0x3d463d22,0x3d553d0e,0x3d623cf1,0x3cc43d6d,0x3cf13d62,0x3d0e3d55,0x3d223d46,0x3d80,0x3bc93d7f,0x3c483d7b,0x3c953d75,
0xbd800000,0xbbc93d7f,0x3d7b3c48,0x3c95bd75,0xbd6dbcc4,0xbcf13d62,0x3d553d0e,0x3d22bd46,0xbd35bd35,0xbd463d22,0x3d0e3d55,0x3d62bcf1,0xbcc4bd6d,0xbd753c95,0x3c483d7b,0x3d7fbbc9,
0x8000bd80,0xbd7fbbc9,0xbc483d7b,0x3d753c95,0x3cc4bd6d,0xbd62bcf1,0xbd0e3d55,0x3d463d22,0x3d35bd35,0xbd22bd46,0xbd553d0e,0x3cf13d62,0x3d6dbcc4,0xbc95bd75,0xbd7b3c48,0x3bc93d7f,
0xbcc4bd6d,0xbd7f3bc9,0xbc483d7b,0x3d623cf1,0xbd800000,0xbc953d75,0x3d553d0e,0x3d46bd22,0x3d6d3cc4,0x3d22bd46,0xbd0ebd55,0xbd753c95,0x3d35bd35,0xbcf1bd62,0xbd7b3c48,0xbbc93d7f,
0xbd6d3cc4,0x3bc93d7f,0x3d7b3c48,0x3cf1bd62,0x80003d80,0x3d753c95,0x3d0ebd55,0xbd22bd46,0x3cc4bd6d,0xbd46bd22,0xbd553d0e,0x3c953d75,0xbd35bd35,0xbd623cf1,0x3c483d7b,0x3d7f3bc9,
0x3d353d35,0x3d75bc95,0x3c48bd7b,0xbd46bd22,0xbd6d3cc4,0xbbc93d7f,0x3d553d0e,0x3d62bcf1,0xbd800000,0xbcf13d62,0x3d0e3d55,0x3d7fbbc9,0x3cc4bd6d,0xbd22bd46,0xbd7b3c48,0xbc953d75,
0xbd353d35,0x3c953d75,0x3d7b3c48,0x3d22bd46,0xbcc4bd6d,0xbd7fbbc9,0xbd0e3d55,0x3cf13d62,0x8000bd80,0xbd62bcf1,0xbd553d0e,0x3bc93d7f,0x3d6d3cc4,0x3d46bd22,0xbc48bd7b,0xbd75bc95,
0x3cc4bd6d,0xbcf1bd62,0xbd7bbc48,0xbd463d22,0xbd353d35,0x3bc93d7f,0x3d553d0e,0x3d75bc95,0x3d6dbcc4,0x3c95bd75,0xbd0ebd55,0xbd7fbbc9,0xbd800000,0xbd223d46,0x3c483d7b,0x3d623cf1,
0xbd6dbcc4,0xbd623cf1,0xbc483d7b,0x3d223d46,0x3d353d35,0x3d7fbbc9,0x3d0ebd55,0xbc95bd75,0xbcc4bd6d,0xbd75bc95,0xbd553d0e,0xbbc93d7f,0x80003d80,0x3d463d22,0x3d7bbc48,0x3cf1bd62,
0x8000bd80,0xbd22bd46,0xbd7bbc48,0xbd623cf1,0xbcc43d6d,0x3c953d75,0x3d553d0e,0x3d7fbbc9,0x3d35bd35,0x3bc9bd7f,0xbd0ebd55,0xbd75bc95,0xbd6d3cc4,0xbcf13d62,0x3c483d7b,0x3d463d22,
0xbd800000,0xbd463d22,0xbc483d7b,0x3cf13d62,0x3d6d3cc4,0x3d75bc95,0x3d0ebd55,0xbbc9bd7f,0xbd35bd35,0xbd7fbbc9,0xbd553d0e,0xbc953d75,0x3cc43d6d,0x3d623cf1,0x3d7bbc48,0x3d22bd46,
0x3d6dbcc4,0x3d22bd46,0x3c48bd7b,0xbc95bd75,0x80003d80,0x3cf13d62,0x3d553d0e,0x3d7f3bc9,0xbcc43d6d,0x3bc93d7f,0x3d0e3d55,0x3d623cf1,0xbd35bd35,0xbd75bc95,0xbd7b3c48,0xbd463d22,
0x3cc43d6d,0x3d463d22,0x3d7b3c48,0x3d75bc95,0xbd800000,0xbd623cf1,0xbd0e3d55,0xbbc93d7f,0xbd6dbcc4,0xbd7f3bc9,0xbd553d0e,0xbcf13d62,0x3d35bd35,0x3c95bd75,0xbc48bd7b,0xbd22bd46,
0xbd353d35,0xbcf13d62,0xbc483d7b,0x3bc93d7f,0x3cc43d6d,0x3d223d46,0x3d553d0e,0x3d753c95,0x8000bd80,0xbc95bd75,0xbd0ebd55,0xbd46bd22,0xbd6dbcc4,0xbd7fbbc9,0xbd7b3c48,0xbd623cf1,
0x3d353d35,0x3d623cf1,0x3d7b3c48,0x3d7fbbc9,0x3d6dbcc4,0x3d46bd22,0x3d0ebd55,0x3c95bd75,0xbd800000,0xbd753c95,0xbd553d0e,0xbd223d46,0xbcc43d6d,0xbbc93d7f,0x3c483d7b,0x3cf13d62,
0x3d6d3cc4,0x3d753c95,0x3d7b3c48,0x3d7f3bc9,0x3d353d35,0x3d463d22,0x3d553d0e,0x3d623cf1,0x3cc43d6d,0x3cf13d62,0x3d0e3d55,0x3d223d46,0x80003d80,0x3bc93d7f,0x3c483d7b,0x3c953d75,
0xbcc43d6d,0xbc953d75,0xbc483d7b,0xbbc93d7f,0xbd353d35,0xbd223d46,0xbd0e3d55,0xbcf13d62,0xbd6d3cc4,0xbd623cf1,0xbd553d0e,0xbd463d22,0xbd800000,0xbd7f3bc9,0xbd7b3c48,0xbd753c95,
0x3d80,0xbc163d7d,0xbc953d75,0xbcdb3d67,0xbd0e3d55,0xbd2c3d3e,0xbd463d22,0xbd5c3d04,0xbd6d3cc4,0xbd783c79,0xbd7f3bc9,0xbd80bb49,0xbd7bbc48,0xbd71bcac,0xbd62bcf1,0xbd4ebd18,
0xbd35bd35,0xbd18bd4e,0xbcf1bd62,0xbcacbd71,0xbc48bd7b,0xbb49bd80,0x3bc9bd7f,0x3c79bd78,0x3cc4bd6d,0x3d04bd5c,0x3d22bd46,0x3d3ebd2c,0x3d55bd0e,0x3d67bcdb,0x3d75bc95,0x3d7dbc16,
0xbd7b3c48,0xbd7dbc16,0xbd62bcf1,0xbd2cbd3e,0x3d80,0xbcac3d71,0xbd223d46,0xbd5c3d04,0x3d55bd0e,0x3d78bc79,0x3d7f3bc9,0x3d673cdb,0xbcc4bd6d,0xbb49bd80,0x3c95bd75,0x3d18bd4e,
0xbd0e3d55,0xbd4e3d18,0xbd753c95,0xbd80bb49,0x3d353d35,0x3cdb3d67,0x3bc93d7f,0xbc793d78,0x3c48bd7b,0x3d04bd5c,0x3d46bd22,0x3d71bcac,0xbd6dbcc4,0xbd3ebd2c,0xbcf1bd62,0xbc16bd7d,
0x3d6dbcc4,0x3d7d3c16,0x3d463d22,0x3cac3d71,0xbc483d7b,0xbd2c3d3e,0xbd753c95,0xbd78bc79,0x3d80,0xbd043d5c,0xbd623cf1,0xbd80bb49,0xbd55bd0e,0xbcdbbd67,0x3bc9bd7f,0x3d18bd4e,
0xbcc43d6d,0xbd4e3d18,0xbd7f3bc9,0xbd67bcdb,0xbd0ebd55,0xbb49bd80,0x3cf1bd62,0x3d5cbd04,0xbd35bd35,0xbc79bd78,0x3c95bd75,0x3d3ebd2c,0x3d7bbc48,0x3d713cac,0x3d223d46,0x3c163d7d,
0xbd0ebd55,0x3c16bd7d,0x3d46bd22,0x3d803b49,0x3cc43d6d,0xbcac3d71,0xbd623cf1,0xbd78bc79,0xbc48bd7b,0x3d04bd5c,0x3d75bc95,0x3d673cdb,0x3d80,0xbd2c3d3e,0xbd7f3bc9,0xbd4ebd18,
0xbd7bbc48,0xbd18bd4e,0x3bc9bd7f,0x3d3ebd2c,0x3d6d3cc4,0x3cdb3d67,0xbc953d75,0xbd5c3d04,0xbd55bd0e,0xbc79bd78,0x3cf1bd62,0x3d71bcac,0x3d353d35,0x3b493d80,0xbd223d46,0xbd7d3c16,
0xbd35bd35,0x3c16bd7d,0x3d62bcf1,0x3d673cdb,0x3c483d7b,0xbd2c3d3e,0xbd7fbbc9,0xbd04bd5c,0x3cc4bd6d,0x3d78bc79,0x3d463d22,0xbb493d80,0xbd553d0e,0xbd71bcac,0xbc95bd75,0x3d18bd4e,
0x3d80,0xbd4e3d18,0xbd75bc95,0xbcacbd71,0x3d0ebd55,0x3d80bb49,0x3d223d46,0xbc793d78,0xbd6d3cc4,0xbd5cbd04,0xbbc9bd7f,0x3d3ebd2c,0x3d7b3c48,0x3cdb3d67,0xbcf13d62,0xbd7d3c16,
0x3d0ebd55,0x3d7d3c16,0x3c953d75,0xbd3e3d2c,0x3d353d35,0xbcac3d71,0xbd7f3bc9,0xbd04bd5c,0xbc483d7b,0xbd783c79,0xbd22bd46,0x3cdbbd67,0xbd6dbcc4,0xbb49bd80,0x3d62bcf1,0x3d4e3d18,
0x3d7bbc48,0x3d183d4e,0xbcf13d62,0xbd80bb49,0x3d80,0xbd673cdb,0xbd46bd22,0x3c79bd78,0xbd553d0e,0xbd5cbd04,0x3bc9bd7f,0x3d71bcac,0xbcc4bd6d,0x3d2cbd3e,0x3d753c95,0x3c163d7d,
0xbcc43d6d,0xbd7dbc16,0xbbc9bd7f,0x3d71bcac,0x3d0e3d55,0xbd2c3d3e,0xbd62bcf1,0x3c79bd78,0xbd35bd35,0x3d04bd5c,0x3d753c95,0xbb493d80,0xbd7b3c48,0xbcdbbd67,0x3d46bd22,0x3d4e3d18,
0x3d6dbcc4,0x3d183d4e,0xbd223d46,0xbd67bcdb,0x3c48bd7b,0x3d80bb49,0x3c953d75,0xbd5c3d04,0x3d80,0xbd783c79,0xbcf1bd62,0x3d3ebd2c,0x3d553d0e,0xbcac3d71,0xbd7fbbc9,0xbc16bd7d,
0x3d7b3c48,0xbc163d7d,0xbd7fbbc9,0x3b49bd80,0x3d6d3cc4,0xbcac3d71,0xbd75bc95,0x3c79bd78,0x3d553d0e,0xbd043d5c,0xbd62bcf1,0x3cdbbd67,0x3d353d35,0xbd2c3d3e,0xbd46bd22,0x3d18bd4e,
0x3d0e3d55,0xbd4e3d18,0xbd22bd46,0x3d3ebd2c,0x3cc43d6d,0xbd673cdb,0xbcf1bd62,0x3d5cbd04,0x3c483d7b,0xbd783c79,0xbc95bd75,0x3d71bcac,0x3d80,0xbd803b49,0xbbc9bd7f,0x3d7dbc16,
0xbd800000,0xbd7dbc16,0xbd75bc95,0xbd67bcdb,0xbd55bd0e,0xbd3ebd2c,0xbd22bd46,0xbd04bd5c,0xbcc4bd6d,0xbc79bd78,0xbbc9bd7f,0x3b49bd80,0x3c48bd7b,0x3cacbd71,0x3cf1bd62,0x3d18bd4e,
0x3d35bd35,0x3d4ebd18,0x3d62bcf1,0x3d71bcac,0x3d7bbc48,0x3d80bb49,0x3d7f3bc9,0x3d783c79,0x3d6d3cc4,0x3d5c3d04,0x3d463d22,0x3d2c3d3e,0x3d0e3d55,0x3cdb3d67,0x3c953d75,0x3c163d7d,
0xbc48bd7b,0x3c16bd7d,0x3cf1bd62,0x3d3ebd2c,0xbd800000,0xbd71bcac,0xbd46bd22,0xbd04bd5c,0x3d0e3d55,0x3c793d78,0xbbc93d7f,0xbcdb3d67,0x3d6dbcc4,0x3d80bb49,0x3d753c95,0x3d4e3d18,
0xbd55bd0e,0xbd18bd4e,0xbc95bd75,0x3b49bd80,0xbd353d35,0xbd673cdb,0xbd7f3bc9,0xbd78bc79,0x3d7b3c48,0x3d5c3d04,0x3d223d46,0x3cac3d71,0x3cc4bd6d,0x3d2cbd3e,0x3d62bcf1,0x3d7dbc16,
0x3cc43d6d,0xbc163d7d,0xbd223d46,0xbd713cac,0xbd7bbc48,0xbd3ebd2c,0xbc95bd75,0x3c79bd78,0xbd800000,0xbd5cbd04,0xbcf1bd62,0x3b49bd80,0x3d0ebd55,0x3d67bcdb,0x3d7f3bc9,0x3d4e3d18,
0xbd6dbcc4,0xbd18bd4e,0xbbc9bd7f,0x3cdbbd67,0x3d55bd0e,0x3d80bb49,0x3d623cf1,0x3d043d5c,0x3d35bd35,0x3d78bc79,0x3d753c95,0x3d2c3d3e,0x3c483d7b,0xbcac3d71,0xbd463d22,0xbd7d3c16,
0x3d55bd0e,0x3d7d3c16,0x3d223d46,0xbb493d80,0xbd6d3cc4,0xbd71bcac,0xbcf1bd62,0x3c79bd78,0x3d7bbc48,0x3d5c3d04,0x3c953d75,0xbcdb3d67,0xbd800000,0xbd3ebd2c,0xbbc9bd7f,0x3d18bd4e,
0x3c48bd7b,0x3d4ebd18,0x3d7f3bc9,0x3d2c3d3e,0xbcc43d6d,0xbd673cdb,0xbd75bc95,0xbd04bd5c,0x3d0ebd55,0x3d78bc79,0x3d623cf1,0x3cac3d71,0xbd353d35,0xbd803b49,0xbd46bd22,0xbc16bd7d,
0x3d35bd35,0x3d7d3c16,0x3cf13d62,0xbcdb3d67,0xbd7b3c48,0xbd3ebd2c,0x3bc9bd7f,0x3d5cbd04,0x3d6d3cc4,0x3c793d78,0xbd223d46,0xbd80bb49,0xbd0ebd55,0x3cacbd71,0x3d75bc95,0x3d4e3d18,
0xbd800000,0xbd18bd4e,0x3c95bd75,0x3d71bcac,0x3d553d0e,0x3b493d80,0xbd463d22,0xbd78bc79,0xbcc4bd6d,0x3d04bd5c,0x3d7fbbc9,0x3d2c3d3e,0xbc483d7b,0xbd673cdb,0xbd62bcf1,0xbc16bd7d,
0x3d553d0e,0xbc163d7d,0xbd753c95,0xbd2cbd3e,0xbd353d35,0xbd71bcac,0xbbc9bd7f,0x3d5cbd04,0xbd7bbc48,0xbc79bd78,0x3d46bd22,0x3d673cdb,0x3cc4bd6d,0x3d80bb49,0x3cf13d62,0xbd183d4e,
0x3c483d7b,0xbd4e3d18,0xbd62bcf1,0x3b49bd80,0xbd800000,0xbcdbbd67,0x3d22bd46,0x3d783c79,0xbd0ebd55,0x3d04bd5c,0x3d7f3bc9,0x3cac3d71,0x3d6dbcc4,0x3d3e3d2c,0xbc953d75,0xbd7d3c16,
0xbd6dbcc4,0x3c16bd7d,0x3d7fbbc9,0x3cac3d71,0xbd553d0e,0xbd3ebd2c,0x3cf1bd62,0x3d783c79,0x3d35bd35,0x3d5c3d04,0xbc953d75,0xbd80bb49,0xbc48bd7b,0x3d67bcdb,0x3d223d46,0xbd183d4e,
0x3cc43d6d,0xbd4e3d18,0xbd46bd22,0x3cdbbd67,0x3d7b3c48,0x3b493d80,0xbd753c95,0xbd04bd5c,0xbd800000,0xbc79bd78,0x3d62bcf1,0x3d2c3d3e,0xbd0e3d55,0xbd71bcac,0x3bc9bd7f,0x3d7dbc16,
0xbc483d7b,0xbd7dbc16,0x3bc9bd7f,0x3d803b49,0xbcc43d6d,0xbd71bcac,0x3c95bd75,0x3d783c79,0xbd0e3d55,0xbd5cbd04,0x3cf1bd62,0x3d673cdb,0xbd353d35,0xbd3ebd2c,0x3d22bd46,0x3d4e3d18,
0xbd553d0e,0xbd18bd4e,0x3d46bd22,0x3d2c3d3e,0xbd6d3cc4,0xbcdbbd67,0x3d62bcf1,0x3d043d5c,0xbd7b3c48,0xbc79bd78,0x3d75bc95,0x3cac3d71,0xbd800000,0xbb49bd80,0x3d7fbbc9,0x3c163d7d,
0x3d80,0xbd7dbc16,0x3c95bd75,0x3d673cdb,0xbd0e3d55,0xbd3ebd2c,0x3d46bd22,0x3d043d5c,0xbd6d3cc4,0xbc79bd78,0x3d7fbbc9,0xbb493d80,0xbd7bbc48,0x3cacbd71,0x3d623cf1,0xbd183d4e,
0xbd35bd35,0x3d4ebd18,0x3cf13d62,0xbd713cac,0xbc48bd7b,0x3d80bb49,0xbbc93d7f,0xbd78bc79,0x3cc4bd6d,0x3d5c3d04,0xbd223d46,0xbd2cbd3e,0x3d55bd0e,0x3cdb3d67,0xbd753c95,0xbc16bd7d,
0xbd7b3c48,0x3c16bd7d,0x3d623cf1,0xbd3e3d2c,0x3d80,0xbd71bcac,0x3d22bd46,0x3d043d5c,0x3d55bd0e,0x3c793d78,0xbd7fbbc9,0x3cdbbd67,0xbcc4bd6d,0x3d80bb49,0xbc953d75,0xbd4ebd18,
0xbd0e3d55,0xbd18bd4e,0x3d75bc95,0xbb493d80,0x3d353d35,0xbd673cdb,0xbbc9bd7f,0x3d783c79,0x3c48bd7b,0x3d5c3d04,0xbd463d22,0xbcacbd71,0xbd6dbcc4,0x3d2cbd3e,0x3cf13d62,0xbd7d3c16,
0x3d6dbcc4,0xbc163d7d,0xbd46bd22,0x3d71bcac,0xbc483d7b,0xbd3ebd2c,0x3d75bc95,0xbc793d78,0x3d80,0xbd5cbd04,0x3d62bcf1,0xbb493d80,0xbd55bd0e,0x3d67bcdb,0xbbc93d7f,0xbd4ebd18,
0xbcc43d6d,0xbd18bd4e,0x3d7fbbc9,0xbcdb3d67,0xbd0ebd55,0x3d80bb49,0xbcf13d62,0xbd04bd5c,0xbd35bd35,0x3d78bc79,0xbc953d75,0xbd2cbd3e,0x3d7bbc48,0xbcac3d71,0xbd22bd46,0x3d7dbc16,
0xbd0ebd55,0x3d7d3c16,0xbd463d22,0x3b49bd80,0x3cc43d6d,0xbd71bcac,0x3d62bcf1,0xbc793d78,0xbc48bd7b,0x3d5c3d04,0xbd753c95,0x3cdbbd67,0x3d80,0xbd3ebd2c,0x3d7fbbc9,0xbd183d4e,
0xbd7bbc48,0x3d4ebd18,0xbbc93d7f,0xbd2cbd3e,0x3d6d3cc4,0xbd673cdb,0x3c95bd75,0x3d043d5c,0xbd55bd0e,0x3d78bc79,0xbcf13d62,0xbcacbd71,0x3d353d35,0xbd803b49,0x3d22bd46,0x3c163d7d,
0xbd35bd35,0x3d7d3c16,0xbd623cf1,0x3cdbbd67,0x3c483d7b,0xbd3ebd2c,0x3d7f3bc9,0xbd5c3d04,0x3cc4bd6d,0x3c793d78,0xbd46bd22,0x3d803b49,0xbd553d0e,0x3cacbd71,0x3c953d75,0xbd4ebd18,
0x3d80,0xbd18bd4e,0x3d753c95,0xbd713cac,0x3d0ebd55,0x3b493d80,0xbd22bd46,0x3d783c79,0xbd6d3cc4,0x3d04bd5c,0x3bc93d7f,0xbd2cbd3e,0x3d7b3c48,0xbd673cdb,0x3cf1bd62,0x3c163d7d,
0x3d0ebd55,0xbc163d7d,0xbc95bd75,0x3d2c3d3e,0x3d353d35,0xbd71bcac,0x3d7fbbc9,0xbd5c3d04,0xbc483d7b,0xbc79bd78,0x3d223d46,0xbd67bcdb,0xbd6dbcc4,0x3d80bb49,0xbd623cf1,0x3d18bd4e,
0x3d7bbc48,0xbd4e3d18,0x3cf1bd62,0xbb493d80,0x3d80,0xbcdbbd67,0x3d463d22,0xbd78bc79,0xbd553d0e,0x3d04bd5c,0xbbc93d7f,0xbcacbd71,0xbcc4bd6d,0x3d3e3d2c,0xbd75bc95,0x3d7dbc16,
0xbcc43d6d,0x3c16bd7d,0x3bc93d7f,0xbcacbd71,0x3d0e3d55,0xbd3ebd2c,0x3d623cf1,0xbd78bc79,0xbd35bd35,0x3d5c3d04,0xbd75bc95,0x3d803b49,0xbd7b3c48,0x3d67bcdb,0xbd463d22,0x3d18bd4e,
0x3d6dbcc4,0xbd4e3d18,0x3d22bd46,0xbcdb3d67,0x3c48bd7b,0x3b493d80,0xbc95bd75,0x3d043d5c,0x3d80,0xbc79bd78,0x3cf13d62,0xbd2cbd3e,0x3d553d0e,0xbd71bcac,0x3d7f3bc9,0xbd7d3c16,
0x3d7b3c48,0xbd7dbc16,0x3d7f3bc9,0xbd80bb49,0x3d6d3cc4,0xbd71bcac,0x3d753c95,0xbd78bc79,0x3d553d0e,0xbd5cbd04,0x3d623cf1,0xbd67bcdb,0x3d353d35,0xbd3ebd2c,0x3d463d22,0xbd4ebd18,
0x3d0e3d55,0xbd18bd4e,0x3d223d46,0xbd2cbd3e,0x3cc43d6d,0xbcdbbd67,0x3cf13d62,0xbd04bd5c,0x3c483d7b,0xbc79bd78,0x3c953d75,0xbcacbd71,0x3d80,0xbb49bd80,0x3bc93d7f,0xbc16bd7d,
0xbd800000,0x3c16bd7d,0x3d753c95,0xbcdb3d67,0xbd55bd0e,0x3d2cbd3e,0x3d223d46,0xbd5c3d04,0xbcc4bd6d,0x3d78bc79,0x3bc93d7f,0xbd80bb49,0x3c48bd7b,0x3d713cac,0xbcf13d62,0xbd4ebd18,
0x3d35bd35,0x3d183d4e,0xbd623cf1,0xbcacbd71,0x3d7bbc48,0x3b493d80,0xbd7fbbc9,0x3c79bd78,0x3d6d3cc4,0xbd043d5c,0xbd46bd22,0x3d3ebd2c,0x3d0e3d55,0xbd673cdb,0xbc95bd75,0x3d7dbc16,
0xbc48bd7b,0x3d7d3c16,0xbcf13d62,0xbd2cbd3e,0xbd800000,0x3cacbd71,0x3d463d22,0xbd5c3d04,0x3d0e3d55,0xbd783c79,0x3bc9bd7f,0x3d673cdb,0x3d6dbcc4,0x3b493d80,0xbd75bc95,0x3d18bd4e,
0xbd55bd0e,0x3d4ebd18,0x3c953d75,0xbd80bb49,0xbd353d35,0xbcdbbd67,0x3d7fbbc9,0xbc793d78,0x3d7b3c48,0xbd043d5c,0xbd22bd46,0x3d71bcac,0x3cc4bd6d,0x3d3e3d2c,0xbd623cf1,0xbc16bd7d,
0x3cc43d6d,0xbd7dbc16,0x3d22bd46,0x3cac3d71,0xbd7bbc48,0x3d2cbd3e,0x3c953d75,0xbd78bc79,0xbd800000,0x3d04bd5c,0x3cf13d62,0xbd80bb49,0x3d0ebd55,0x3cdb3d67,0xbd7fbbc9,0x3d18bd4e,
0xbd6dbcc4,0x3d4ebd18,0x3bc93d7f,0xbd67bcdb,0x3d55bd0e,0x3b493d80,0xbd62bcf1,0x3d5cbd04,0x3d35bd35,0x3c793d78,0xbd75bc95,0x3d3ebd2c,0x3c483d7b,0xbd71bcac,0x3d46bd22,0x3c163d7d,
0x3d55bd0e,0xbc163d7d,0xbd22bd46,0x3d803b49,0xbd6d3cc4,0x3cacbd71,0x3cf13d62,0xbd78bc79,0x3d7bbc48,0xbd043d5c,0xbc95bd75,0x3d673cdb,0xbd800000,0x3d2cbd3e,0x3bc93d7f,0xbd4ebd18,
0x3c48bd7b,0x3d183d4e,0xbd7fbbc9,0x3d3ebd2c,0xbcc43d6d,0xbcdbbd67,0x3d753c95,0xbd5c3d04,0x3d0ebd55,0x3c793d78,0xbd62bcf1,0x3d71bcac,0xbd353d35,0xbb49bd80,0x3d463d22,0xbd7d3c16,
0x3d35bd35,0xbc163d7d,0xbcf1bd62,0x3d673cdb,0xbd7b3c48,0x3d2cbd3e,0xbbc93d7f,0xbd04bd5c,0x3d6d3cc4,0xbd783c79,0x3d22bd46,0xbb493d80,0xbd0ebd55,0x3d713cac,0xbd753c95,0x3d18bd4e,
0xbd800000,0x3d4ebd18,0xbc953d75,0xbcacbd71,0x3d553d0e,0xbd803b49,0x3d46bd22,0xbc793d78,0xbcc4bd6d,0x3d5c3d04,0xbd7f3bc9,0x3d3ebd2c,0xbc483d7b,0xbcdbbd67,0x3d623cf1,0xbd7d3c16,
0x3d553d0e,0xbd7dbc16,0x3d75bc95,0xbd3e3d2c,0xbd353d35,0x3cacbd71,0x3bc93d7f,0xbd04bd5c,0xbd7bbc48,0x3d78bc79,0xbd463d22,0x3cdbbd67,0x3cc4bd6d,0x3b493d80,0xbcf1bd62,0x3d4e3d18,
0x3c483d7b,0xbd18bd4e,0x3d623cf1,0xbd80bb49,0xbd800000,0x3d67bcdb,0xbd223d46,0x3c79bd78,0xbd0ebd55,0x3d5c3d04,0xbd7fbbc9,0x3d71bcac,0x3d6dbcc4,0xbd2c3d3e,0x3c95bd75,0x3c163d7d,
0xbd6dbcc4,0x3d7d3c16,0xbd7f3bc9,0x3d71bcac,0xbd553d0e,0x3d2cbd3e,0xbcf13d62,0x3c79bd78,0x3d35bd35,0xbd043d5c,0x3c95bd75,0xbb493d80,0xbc48bd7b,0x3cdb3d67,0xbd22bd46,0x3d4e3d18,
0x3cc43d6d,0xbd18bd4e,0x3d463d22,0xbd67bcdb,0x3d7b3c48,0xbd803b49,0x3d75bc95,0xbd5c3d04,0xbd800000,0x3d78bc79,0xbd623cf1,0x3d3ebd2c,0xbd0e3d55,0x3cacbd71,0xbbc93d7f,0xbc16bd7d,
0xbc483d7b,0x3c16bd7d,0xbbc93d7f,0x3b49bd80,0xbcc43d6d,0x3cacbd71,0xbc953d75,0x3c79bd78,0xbd0e3d55,0x3d04bd5c,0xbcf13d62,0x3cdbbd67,0xbd353d35,0x3d2cbd3e,0xbd223d46,0x3d18bd4e,
0xbd553d0e,0x3d4ebd18,0xbd463d22,0x3d3ebd2c,0xbd6d3cc4,0x3d67bcdb,0xbd623cf1,0x3d5cbd04,0xbd7b3c48,0x3d78bc79,0xbd753c95,0x3d71bcac,0xbd800000,0x3d80bb49,0xbd7f3bc9,0x3d7dbc16,
0x3d80,0x3c16bd7d,0xbc953d75,0x3cdbbd67,0xbd0e3d55,0x3d2cbd3e,0xbd463d22,0x3d5cbd04,0xbd6d3cc4,0x3d78bc79,0xbd7f3bc9,0x3d803b49,0xbd7bbc48,0x3d713cac,0xbd62bcf1,0x3d4e3d18,
0xbd35bd35,0x3d183d4e,0xbcf1bd62,0x3cac3d71,0xbc48bd7b,0x3b493d80,0x3bc9bd7f,0xbc793d78,0x3cc4bd6d,0xbd043d5c,0x3d22bd46,0xbd3e3d2c,0x3d55bd0e,0xbd673cdb,0x3d75bc95,0xbd7d3c16,
0xbd7b3c48,0x3d7d3c16,0xbd62bcf1,0x3d2c3d3e,0x3d80,0x3cacbd71,0xbd223d46,0x3d5cbd04,0x3d55bd0e,0xbd783c79,0x3d7f3bc9,0xbd67bcdb,0xbcc4bd6d,0x3b493d80,0x3c95bd75,0xbd183d4e,
0xbd0e3d55,0x3d4ebd18,0xbd753c95,0x3d803b49,0x3d353d35,0xbcdbbd67,0x3bc93d7f,0x3c79bd78,0x3c48bd7b,0xbd043d5c,0x3d46bd22,0xbd713cac,0xbd6dbcc4,0x3d3e3d2c,0xbcf1bd62,0x3c163d7d,
0x3d6dbcc4,0xbd7dbc16,0x3d463d22,0xbcacbd71,0xbc483d7b,0x3d2cbd3e,0xbd753c95,0x3d783c79,0x3d80,0x3d04bd5c,0xbd623cf1,0x3d803b49,0xbd55bd0e,0x3cdb3d67,0x3bc9bd7f,0xbd183d4e,
0xbcc43d6d,0x3d4ebd18,0xbd7f3bc9,0x3d673cdb,0xbd0ebd55,0x3b493d80,0x3cf1bd62,0xbd5c3d04,0xbd35bd35,0x3c793d78,0x3c95bd75,0xbd3e3d2c,0x3d7bbc48,0xbd71bcac,0x3d223d46,0xbc16bd7d,
0xbd0ebd55,0xbc163d7d,0x3d46bd22,0xbd80bb49,0x3cc43d6d,0x3cacbd71,0xbd623cf1,0x3d783c79,0xbc48bd7b,0xbd043d5c,0x3d75bc95,0xbd67bcdb,0x3d80,0x3d2cbd3e,0xbd7f3bc9,0x3d4e3d18,
0xbd7bbc48,0x3d183d4e,0x3bc9bd7f,0xbd3e3d2c,0x3d6d3cc4,0xbcdbbd67,0xbc953d75,0x3d5cbd04,0xbd55bd0e,0x3c793d78,0x3cf1bd62,0xbd713cac,0x3d353d35,0xbb49bd80,0xbd223d46,0x3d7dbc16,
0xbd35bd35,0xbc163d7d,0x3d62bcf1,0xbd67bcdb,0x3c483d7b,0x3d2cbd3e,0xbd7fbbc9,0x3d043d5c,0x3cc4bd6d,0xbd783c79,0x3d463d22,0x3b49bd80,0xbd553d0e,0x3d713cac,0xbc95bd75,0xbd183d4e,
0x3d80,0x3d4ebd18,0xbd75bc95,0x3cac3d71,0x3d0ebd55,0xbd803b49,0x3d223d46,0x3c79bd78,0xbd6d3cc4,0x3d5c3d04,0xbbc9bd7f,0xbd3e3d2c,0x3d7b3c48,0xbcdbbd67,0xbcf13d62,0x3d7dbc16,
0x3d0ebd55,0xbd7dbc16,0x3c953d75,0x3d3ebd2c,0x3d353d35,0x3cacbd71,0xbd7f3bc9,0x3d043d5c,0xbc483d7b,0x3d78bc79,0xbd22bd46,0xbcdb3d67,0xbd6dbcc4,0x3b493d80,0x3d62bcf1,0xbd4ebd18,
0x3d7bbc48,0xbd18bd4e,0xbcf13d62,0x3d803b49,0x3d80,0x3d67bcdb,0xbd46bd22,0xbc793d78,0xbd553d0e,0x3d5c3d04,0x3bc9bd7f,0xbd713cac,0xbcc4bd6d,0xbd2c3d3e,0x3d753c95,0xbc16bd7d,
0xbcc43d6d,0x3d7d3c16,0xbbc9bd7f,0xbd713cac,0x3d0e3d55,0x3d2cbd3e,0xbd62bcf1,0xbc793d78,0xbd35bd35,0xbd043d5c,0x3d753c95,0x3b49bd80,0xbd7b3c48,0x3cdb3d67,0x3d46bd22,0xbd4ebd18,
0x3d6dbcc4,0xbd18bd4e,0xbd223d46,0x3d673cdb,0x3c48bd7b,0xbd803b49,0x3c953d75,0x3d5cbd04,0x3d80,0x3d78bc79,0xbcf1bd62,0xbd3e3d2c,0x3d553d0e,0x3cacbd71,0xbd7fbbc9,0x3c163d7d,
0x3d7b3c48,0x3c16bd7d,0xbd7fbbc9,0xbb493d80,0x3d6d3cc4,0x3cacbd71,0xbd75bc95,0xbc793d78,0x3d553d0e,0x3d04bd5c,0xbd62bcf1,0xbcdb3d67,0x3d353d35,0x3d2cbd3e,0xbd46bd22,0xbd183d4e,
0x3d0e3d55,0x3d4ebd18,0xbd22bd46,0xbd3e3d2c,0x3cc43d6d,0x3d67bcdb,0xbcf1bd62,0xbd5c3d04,0x3c483d7b,0x3d78bc79,0xbc95bd75,0xbd713cac,0x3d80,0x3d80bb49,0xbbc9bd7f,0xbd7d3c16,
0xbd800000,0x3d7d3c16,0xbd75bc95,0x3d673cdb,0xbd55bd0e,0x3d3e3d2c,0xbd22bd46,0x3d043d5c,0xbcc4bd6d,0x3c793d78,0xbbc9bd7f,0xbb493d80,0x3c48bd7b,0xbcac3d71,0x3cf1bd62,0xbd183d4e,
0x3d35bd35,0xbd4e3d18,0x3d62bcf1,0xbd713cac,0x3d7bbc48,0xbd803b49,0x3d7f3bc9,0xbd78bc79,0x3d6d3cc4,0xbd5cbd04,0x3d463d22,0xbd2cbd3e,0x3d0e3d55,0xbcdbbd67,0x3c953d75,0xbc16bd7d,
0xbc48bd7b,0xbc163d7d,0x3cf1bd62,0xbd3e3d2c,0xbd800000,0x3d713cac,0xbd46bd22,0x3d043d5c,0x3d0e3d55,0xbc79bd78,0xbbc93d7f,0x3cdbbd67,0x3d6dbcc4,0xbd803b49,0x3d753c95,0xbd4ebd18,
0xbd55bd0e,0x3d183d4e,0xbc95bd75,0xbb493d80,0xbd353d35,0x3d67bcdb,0xbd7f3bc9,0x3d783c79,0x3d7b3c48,0xbd5cbd04,0x3d223d46,0xbcacbd71,0x3cc4bd6d,0xbd2c3d3e,0x3d62bcf1,0xbd7d3c16,
0x3cc43d6d,0x3c16bd7d,0xbd223d46,0x3d71bcac,0xbd7bbc48,0x3d3e3d2c,0xbc95bd75,0xbc793d78,0xbd800000,0x3d5c3d04,0xbcf1bd62,0xbb493d80,0x3d0ebd55,0xbd673cdb,0x3d7f3bc9,0xbd4ebd18,
0xbd6dbcc4,0x3d183d4e,0xbbc9bd7f,0xbcdb3d67,0x3d55bd0e,0xbd803b49,0x3d623cf1,0xbd04bd5c,0x3d35bd35,0xbd783c79,0x3d753c95,0xbd2cbd3e,0x3c483d7b,0x3cacbd71,0xbd463d22,0x3d7dbc16,
0x3d55bd0e,0xbd7dbc16,0x3d223d46,0x3b49bd80,0xbd6d3cc4,0x3d713cac,0xbcf1bd62,0xbc793d78,0x3d7bbc48,0xbd5cbd04,0x3c953d75,0x3cdbbd67,0xbd800000,0x3d3e3d2c,0xbbc9bd7f,0xbd183d4e,
0x3c48bd7b,0xbd4e3d18,0x3d7f3bc9,0xbd2cbd3e,0xbcc43d6d,0x3d67bcdb,0xbd75bc95,0x3d043d5c,0x3d0ebd55,0xbd783c79,0x3d623cf1,0xbcacbd71,0xbd353d35,0x3d80bb49,0xbd46bd22,0x3c163d7d,
0x3d35bd35,0xbd7dbc16,0x3cf13d62,0x3cdbbd67,0xbd7b3c48,0x3d3e3d2c,0x3bc9bd7f,0xbd5c3d04,0x3d6d3cc4,0xbc79bd78,0xbd223d46,0x3d803b49,0xbd0ebd55,0xbcac3d71,0x3d75bc95,0xbd4ebd18,
0xbd800000,0x3d183d4e,0x3c95bd75,0xbd713cac,0x3d553d0e,0xbb49bd80,0xbd463d22,0x3d783c79,0xbcc4bd6d,0xbd043d5c,0x3d7fbbc9,0xbd2cbd3e,0xbc483d7b,0x3d67bcdb,0xbd62bcf1,0x3c163d7d,
0x3d553d0e,0x3c16bd7d,0xbd753c95,0x3d2c3d3e,0xbd353d35,0x3d713cac,0xbbc9bd7f,0xbd5c3d04,0xbd7bbc48,0x3c793d78,0x3d46bd22,0xbd67bcdb,0x3cc4bd6d,0xbd803b49,0x3cf13d62,0x3d18bd4e,
0x3c483d7b,0x3d4ebd18,0xbd62bcf1,0xbb493d80,0xbd800000,0x3cdb3d67,0x3d22bd46,0xbd78bc79,0xbd0ebd55,0xbd043d5c,0x3d7f3bc9,0xbcacbd71,0x3d6dbcc4,0xbd3ebd2c,0xbc953d75,0x3d7dbc16,
0xbd6dbcc4,0xbc163d7d,0x3d7fbbc9,0xbcacbd71,0xbd553d0e,0x3d3e3d2c,0x3cf1bd62,0xbd78bc79,0x3d35bd35,0xbd5cbd04,0xbc953d75,0x3d803b49,0xbc48bd7b,0xbd673cdb,0x3d223d46,0x3d18bd4e,
0x3cc43d6d,0x3d4ebd18,0xbd46bd22,0xbcdb3d67,0x3d7b3c48,0xbb49bd80,0xbd753c95,0x3d043d5c,0xbd800000,0x3c793d78,0x3d62bcf1,0xbd2cbd3e,0xbd0e3d55,0x3d713cac,0x3bc9bd7f,0xbd7d3c16,
0xbc483d7b,0x3d7d3c16,0x3bc9bd7f,0xbd80bb49,0xbcc43d6d,0x3d713cac,0x3c95bd75,0xbd78bc79,0xbd0e3d55,0x3d5c3d04,0x3cf1bd62,0xbd67bcdb,0xbd353d35,0x3d3e3d2c,0x3d22bd46,0xbd4ebd18,
0xbd553d0e,0x3d183d4e,0x3d46bd22,0xbd2cbd3e,0xbd6d3cc4,0x3cdb3d67,0x3d62bcf1,0xbd04bd5c,0xbd7b3c48,0x3c793d78,0x3d75bc95,0xbcacbd71,0xbd800000,0x3b493d80,0x3d7fbbc9,0xbc16bd7d,
0x3d80,0x3d7d3c16,0x3c95bd75,0xbd67bcdb,0xbd0e3d55,0x3d3e3d2c,0x3d46bd22,0xbd04bd5c,0xbd6d3cc4,0x3c793d78,0x3d7fbbc9,0x3b49bd80,0xbd7bbc48,0xbcac3d71,0x3d623cf1,0x3d18bd4e,
0xbd35bd35,0xbd4e3d18,0x3cf13d62,0x3d71bcac,0xbc48bd7b,0xbd803b49,0xbbc93d7f,0x3d783c79,0x3cc4bd6d,0xbd5cbd04,0xbd223d46,0x3d2c3d3e,0x3d55bd0e,0xbcdbbd67,0xbd753c95,0x3c163d7d,
0xbd7b3c48,0xbc163d7d,0x3d623cf1,0x3d3ebd2c,0x3d80,0x3d713cac,0x3d22bd46,0xbd04bd5c,0x3d55bd0e,0xbc79bd78,0xbd7fbbc9,0xbcdb3d67,0xbcc4bd6d,0xbd803b49,0xbc953d75,0x3d4e3d18,
0xbd0e3d55,0x3d183d4e,0x3d75bc95,0x3b49bd80,0x3d353d35,0x3d67bcdb,0xbbc9bd7f,0xbd78bc79,0x3c48bd7b,0xbd5cbd04,0xbd463d22,0x3cac3d71,0xbd6dbcc4,0xbd2c3d3e,0x3cf13d62,0x3d7dbc16,
0x3d6dbcc4,0x3c16bd7d,0xbd46bd22,0xbd713cac,0xbc483d7b,0x3d3e3d2c,0x3d75bc95,0x3c79bd78,0x3d80,0x3d5c3d04,0x3d62bcf1,0x3b49bd80,0xbd55bd0e,0xbd673cdb,0xbbc93d7f,0x3d4e3d18,
0xbcc43d6d,0x3d183d4e,0x3d7fbbc9,0x3cdbbd67,0xbd0ebd55,0xbd803b49,0xbcf13d62,0x3d043d5c,0xbd35bd35,0xbd783c79,0xbc953d75,0x3d2c3d3e,0x3d7bbc48,0x3cacbd71,0xbd22bd46,0xbd7d3c16,
0xbd0ebd55,0xbd7dbc16,0xbd463d22,0xbb493d80,0x3cc43d6d,0x3d713cac,0x3d62bcf1,0x3c79bd78,0xbc48bd7b,0xbd5cbd04,0xbd753c95,0xbcdb3d67,0x3d80,0x3d3e3d2c,0x3d7fbbc9,0x3d18bd4e,
0xbd7bbc48,0xbd4e3d18,0xbbc93d7f,0x3d2c3d3e,0x3d6d3cc4,0x3d67bcdb,0x3c95bd75,0xbd04bd5c,0xbd55bd0e,0xbd783c79,0xbcf13d62,0x3cac3d71,0x3d353d35,0x3d80bb49,0x3d22bd46,0xbc16bd7d,
0xbd35bd35,0xbd7dbc16,0xbd623cf1,0xbcdb3d67,0x3c483d7b,0x3d3e3d2c,0x3d7f3bc9,0x3d5cbd04,0x3cc4bd6d,0xbc79bd78,0xbd46bd22,0xbd80bb49,0xbd553d0e,0xbcac3d71,0x3c953d75,0x3d4e3d18,
0x3d80,0x3d183d4e,0x3d753c95,0x3d71bcac,0x3d0ebd55,0xbb49bd80,0xbd22bd46,0xbd78bc79,0xbd6d3cc4,0xbd043d5c,0x3bc93d7f,0x3d2c3d3e,0x3d7b3c48,0x3d67bcdb,0x3cf1bd62,0xbc16bd7d,
0x3d0ebd55,0x3c16bd7d,0xbc95bd75,0xbd2cbd3e,0x3d353d35,0x3d713cac,0x3d7fbbc9,0x3d5cbd04,0xbc483d7b,0x3c793d78,0x3d223d46,0x3d673cdb,0xbd6dbcc4,0xbd803b49,0xbd623cf1,0xbd183d4e,
0x3d7bbc48,0x3d4ebd18,0x3cf1bd62,0x3b49bd80,0x3d80,0x3cdb3d67,0x3d463d22,0x3d783c79,0xbd553d0e,0xbd043d5c,0xbbc93d7f,0x3cac3d71,0xbcc4bd6d,0xbd3ebd2c,0xbd75bc95,0xbd7d3c16,
0xbcc43d6d,0xbc163d7d,0x3bc93d7f,0x3cac3d71,0x3d0e3d55,0x3d3e3d2c,0x3d623cf1,0x3d783c79,0xbd35bd35,0xbd5cbd04,0xbd75bc95,0xbd80bb49,0xbd7b3c48,0xbd673cdb,0xbd463d22,0xbd183d4e,
0x3d6dbcc4,0x3d4ebd18,0x3d22bd46,0x3cdbbd67,0x3c48bd7b,0xbb49bd80,0xbc95bd75,0xbd04bd5c,0x3d80,0x3c793d78,0x3cf13d62,0x3d2c3d3e,0x3d553d0e,0x3d713cac,0x3d7f3bc9,0x3d7dbc16,
0x3d7b3c48,0x3d7d3c16,0x3d7f3bc9,0x3d803b49,0x3d6d3cc4,0x3d713cac,0x3d753c95,0x3d783c79,0x3d553d0e,0x3d5c3d04,0x3d623cf1,0x3d673cdb,0x3d353d35,0x3d3e3d2c,0x3d463d22,0x3d4e3d18,
0x3d0e3d55,0x3d183d4e,0x3d223d46,0x3d2c3d3e,0x3cc43d6d,0x3cdb3d67,0x3cf13d62,0x3d043d5c,0x3c483d7b,0x3c793d78,0x3c953d75,0x3cac3d71,0x3d80,0x3b493d80,0x3bc93d7f,0x3c163d7d,
0xbd800000,0xbc163d7d,0x3d753c95,0x3cdbbd67,0xbd55bd0e,0xbd2c3d3e,0x3d223d46,0x3d5cbd04,0xbcc4bd6d,0xbd783c79,0x3bc93d7f,0x3d803b49,0x3c48bd7b,0xbd71bcac,0xbcf13d62,0x3d4e3d18,
0x3d35bd35,0xbd18bd4e,0xbd623cf1,0x3cac3d71,0x3d7bbc48,0xbb49bd80,0xbd7fbbc9,0xbc793d78,0x3d6d3cc4,0x3d04bd5c,0xbd46bd22,0xbd3e3d2c,0x3d0e3d55,0x3d67bcdb,0xbc95bd75,0xbd7d3c16,
0xbc48bd7b,0xbd7dbc16,0xbcf13d62,0x3d2c3d3e,0xbd800000,0xbcac3d71,0x3d463d22,0x3d5cbd04,0x3d0e3d55,0x3d78bc79,0x3bc9bd7f,0xbd67bcdb,0x3d6dbcc4,0xbb49bd80,0xbd75bc95,0xbd183d4e,
0xbd55bd0e,0xbd4e3d18,0x3c953d75,0x3d803b49,0xbd353d35,0x3cdb3d67,0x3d7fbbc9,0x3c79bd78,0x3d7b3c48,0x3d04bd5c,0xbd22bd46,0xbd713cac,0x3cc4bd6d,0xbd3ebd2c,0xbd623cf1,0x3c163d7d,
0x3cc43d6d,0x3d7d3c16,0x3d22bd46,0xbcacbd71,0xbd7bbc48,0xbd2c3d3e,0x3c953d75,0x3d783c79,0xbd800000,0xbd043d5c,0x3cf13d62,0x3d803b49,0x3d0ebd55,0xbcdbbd67,0xbd7fbbc9,0xbd183d4e,
0xbd6dbcc4,0xbd4e3d18,0x3bc93d7f,0x3d673cdb,0x3d55bd0e,0xbb49bd80,0xbd62bcf1,0xbd5c3d04,0x3d35bd35,0xbc79bd78,0xbd75bc95,0xbd3e3d2c,0x3c483d7b,0x3d713cac,0x3d46bd22,0xbc16bd7d,
0x3d55bd0e,0x3c16bd7d,0xbd22bd46,0xbd80bb49,0xbd6d3cc4,0xbcac3d71,0x3cf13d62,0x3d783c79,0x3d7bbc48,0x3d04bd5c,0xbc95bd75,0xbd67bcdb,0xbd800000,0xbd2c3d3e,0x3bc93d7f,0x3d4e3d18,
0x3c48bd7b,0xbd18bd4e,0xbd7fbbc9,0xbd3e3d2c,0xbcc43d6d,0x3cdb3d67,0x3d753c95,0x3d5cbd04,0x3d0ebd55,0xbc79bd78,0xbd62bcf1,0xbd713cac,0xbd353d35,0x3b493d80,0x3d463d22,0x3d7dbc16,
0x3d35bd35,0x3c16bd7d,0xbcf1bd62,0xbd67bcdb,0xbd7b3c48,0xbd2c3d3e,0xbbc93d7f,0x3d043d5c,0x3d6d3cc4,0x3d78bc79,0x3d22bd46,0x3b49bd80,0xbd0ebd55,0xbd71bcac,0xbd753c95,0xbd183d4e,
0xbd800000,0xbd4e3d18,0xbc953d75,0x3cac3d71,0x3d553d0e,0x3d80bb49,0x3d46bd22,0x3c79bd78,0xbcc4bd6d,0xbd5cbd04,0xbd7f3bc9,0xbd3e3d2c,0xbc483d7b,0x3cdb3d67,0x3d623cf1,0x3d7dbc16,
0x3d553d0e,0x3d7d3c16,0x3d75bc95,0x3d3ebd2c,0xbd353d35,0xbcac3d71,0x3bc93d7f,0x3d043d5c,0xbd7bbc48,0xbd783c79,0xbd463d22,0xbcdb3d67,0x3cc4bd6d,0xbb49bd80,0xbcf1bd62,0xbd4ebd18,
0x3c483d7b,0x3d183d4e,0x3d623cf1,0x3d803b49,0xbd800000,0xbd673cdb,0xbd223d46,0xbc793d78,0xbd0ebd55,0xbd5cbd04,0xbd7fbbc9,0xbd713cac,0x3d6dbcc4,0x3d2cbd3e,0x3c95bd75,0xbc16bd7d,
0xbd6dbcc4,0xbd7dbc16,0xbd7f3bc9,0xbd713cac,0xbd553d0e,0xbd2c3d3e,0xbcf13d62,0xbc793d78,0x3d35bd35,0x3d04bd5c,0x3c95bd75,0x3b49bd80,0xbc48bd7b,0xbcdbbd67,0xbd22bd46,0xbd4ebd18,
0x3cc43d6d,0x3d183d4e,0x3d463d22,0x3d673cdb,0x3d7b3c48,0x3d80bb49,0x3d75bc95,0x3d5cbd04,0xbd800000,0xbd783c79,0xbd623cf1,0xbd3e3d2c,0xbd0e3d55,0xbcac3d71,0xbbc93d7f,0x3c163d7d,
0xbc483d7b,0xbc163d7d,0xbbc93d7f,0xbb493d80,0xbcc43d6d,0xbcac3d71,0xbc953d75,0xbc793d78,0xbd0e3d55,0xbd043d5c,0xbcf13d62,0xbcdb3d67,0xbd353d35,0xbd2c3d3e,0xbd223d46,0xbd183d4e,
0xbd553d0e,0xbd4e3d18,0xbd463d22,0xbd3e3d2c,0xbd6d3cc4,0xbd673cdb,0xbd623cf1,0xbd5c3d04,0xbd7b3c48,0xbd783c79,0xbd753c95,0xbd713cac,0xbd800000,0xbd803b49,0xbd7f3bc9,0xbd7d3c16,
0x3f003f00,0xbf003f00,0x3f003f00,0xbf003f00,0x3f003f00,0xbf003f00,0x3f003f00,0xbf003f00,0x3f003f00,0xbf003f00,0x3f003f00,0xbf003f00,0x3f003f00,0xbf003f00,0x3f003f00,0xbf003f00,
0x3eff3f00,0xbd490000,0x3ea23eb5,0xbec6beb5,0x3ef53efb,0xbe15bdc8,0x3e713e8e,0xbee2bed5,0x3ee23eed,0xbe71be44,0x3e153e44,0xbef5beed,0x3ec63ed5,0xbea2be8e,0x3d493dc8,0xbeffbefb,
0x3efb3f00,0xbdc80000,0xbdc80000,0xbefbbf00,0x3ed53eed,0xbe8ebe44,0xbe8ebe44,0xbed5beed,0x3e8e3eb5,0xbed5beb5,0xbed5beb5,0xbe8ebeb5,0x3dc83e44,0xbefbbeed,0xbefbbeed,0xbdc8be44,
0x3ef53f00,0xbe150000,0xbee2beb5,0xbe71beb5,0x3ea23ed5,0xbec6be8e,0xbeffbefb,0x3d49bdc8,0x3d493e44,0xbeffbeed,0xbec6beed,0x3ea23e44,0xbe71bdc8,0xbee2befb,0xbe15be8e,0x3ef53ed5,
0x3eed3f00,0xbe440000,0xbeedbf00,0x3e440000,0x3e443eb5,0xbeedbeb5,0xbe44beb5,0x3eed3eb5,0xbe440000,0xbeedbf00,0x3e440000,0x3eed3f00,0xbeedbeb5,0xbe44beb5,0x3eed3eb5,0x3e443eb5,
0x3ee23f00,0xbe710000,0xbe15beb5,0x3ef53eb5,0x3d493e8e,0xbeffbed5,0x3ea23dc8,0x3ec63efb,0xbec6be44,0xbea2beed,0x3eff3eed,0xbd493e44,0xbef5befb,0x3e15bdc8,0x3e713ed5,0xbee2be8e,
0x3ed53f00,0xbe8e0000,0x3e8e0000,0x3ed53f00,0xbdc83e44,0xbefbbeed,0x3efb3eed,0xbdc83e44,0xbefbbeb5,0xbdc8beb5,0x3dc83eb5,0xbefbbeb5,0xbe8ebeed,0x3ed53e44,0xbed5be44,0xbe8ebeed,
0x3ec63f00,0xbea20000,0x3eff3eb5,0x3d493eb5,0xbe713dc8,0xbee2befb,0x3e153ed5,0xbef5be8e,0xbef5beed,0x3e15be44,0xbee2be44,0xbe71beed,0x3d49be8e,0x3eff3ed5,0xbea2befb,0x3ec63dc8,
0x3f00,0xbf000000,0x3f00,0xbf000000,0xbf00,0x3f000000,0xbf00,0x3f000000,0x3f00,0xbf000000,0x3f00,0xbf000000,0xbf00,0x3f000000,0xbf00,0x3f000000,
0xbd493f00,0xbeff0000,0xbec63eb5,0xbea2beb5,0x3e15befb,0x3ef53dc8,0x3ee2be8e,0x3e713ed5,0xbe713eed,0xbee2be44,0xbef53e44,0xbe15beed,0x3ea2bed5,0x3ec63e8e,0x3effbdc8,0x3d493efb,
0xbdc83f00,0xbefb0000,0xbefb0000,0x3dc8bf00,0x3e8ebeed,0x3ed53e44,0x3ed53e44,0xbe8e3eed,0xbed53eb5,0xbe8ebeb5,0xbe8ebeb5,0x3ed5beb5,0x3efbbe44,0x3dc83eed,0x3dc83eed,0xbefb3e44,
0xbe153f00,0xbef50000,0xbe71beb5,0x3ee2beb5,0x3ec6bed5,0x3ea23e8e,0xbd493efb,0xbeff3dc8,0xbeff3e44,0xbd49beed,0x3ea2beed,0x3ec63e44,0x3ee23dc8,0xbe713efb,0xbef53e8e,0xbe15bed5,
0xbe443f00,0xbeed0000,0x3e44bf00,0x3eed0000,0x3eedbeb5,0x3e443eb5,0xbeed3eb5,0xbe44beb5,0xbeed0000,0x3e44bf00,0x3eed0000,0xbe443f00,0x3e443eb5,0xbeed3eb5,0xbe44beb5,0x3eedbeb5,
0xbe713f00,0xbee20000,0x3ef5beb5,0x3e153eb5,0x3effbe8e,0x3d493ed5,0xbec6bdc8,0x3ea2befb,0xbea2be44,0x3ec6beed,0xbd493eed,0xbeff3e44,0xbe153efb,0xbef53dc8,0x3ee2bed5,0x3e713e8e,
0xbe8e3f00,0xbed50000,0x3ed50000,0xbe8e3f00,0x3efbbe44,0xbdc83eed,0x3dc8beed,0x3efbbe44,0xbdc8beb5,0x3efbbeb5,0xbefb3eb5,0xbdc8beb5,0xbed53eed,0xbe8ebe44,0x3e8e3e44,0xbed53eed,
0xbea23f00,0xbec60000,0x3d493eb5,0xbeff3eb5,0x3ee2bdc8,0xbe713efb,0x3ef5bed5,0x3e153e8e,0x3e15beed,0x3ef5be44,0xbe71be44,0x3ee2beed,0xbeff3e8e,0x3d49bed5,0xbec63efb,0xbea2bdc8,
0x3eb53f00,0xbeb50000,0x3eb53f00,0xbeb50000,0xbeb50000,0xbeb5bf00,0xbeb50000,0xbeb5bf00,0xbeb5bf00,0x3eb50000,0xbeb5bf00,0x3eb50000,0x3eb50000,0x3eb53f00,0x3eb50000,0x3eb53f00,
0xbeff3f00,0x3d490000,0xbea23eb5,0x3ec6beb5,0xbef53efb,0x3e15bdc8,0xbe713e8e,0x3ee2bed5,0xbee23eed,0x3e71be44,0xbe153e44,0x3ef5beed,0xbec63ed5,0x3ea2be8e,0xbd493dc8,0x3effbefb,
0xbefb3f00,0x3dc80000,0x3dc80000,0x3efbbf00,0xbed53eed,0x3e8ebe44,0x3e8ebe44,0x3ed5beed,0xbe8e3eb5,0x3ed5beb5,0x3ed5beb5,0x3e8ebeb5,0xbdc83e44,0x3efbbeed,0x3efbbeed,0x3dc8be44,
0xbef53f00,0x3e150000,0x3ee2beb5,0x3e71beb5,0xbea23ed5,0x3ec6be8e,0x3effbefb,0xbd49bdc8,0xbd493e44,0x3effbeed,0x3ec6beed,0xbea23e44,0x3e71bdc8,0x3ee2befb,0x3e15be8e,0xbef53ed5,
0xbeed3f00,0x3e440000,0x3eedbf00,0xbe440000,0xbe443eb5,0x3eedbeb5,0x3e44beb5,0xbeed3eb5,0x3e440000,0x3eedbf00,0xbe440000,0xbeed3f00,0x3eedbeb5,0x3e44beb5,0xbeed3eb5,0xbe443eb5,
0xbee23f00,0x3e710000,0x3e15beb5,0xbef53eb5,0xbd493e8e,0x3effbed5,0xbea23dc8,0xbec63efb,0x3ec6be44,0x3ea2beed,0xbeff3eed,0x3d493e44,0x3ef5befb,0xbe15bdc8,0xbe713ed5,0x3ee2be8e,
0xbed53f00,0x3e8e0000,0xbe8e0000,0xbed53f00,0x3dc83e44,0x3efbbeed,0xbefb3eed,0x3dc83e44,0x3efbbeb5,0x3dc8beb5,0xbdc83eb5,0x3efbbeb5,0x3e8ebeed,0xbed53e44,0x3ed5be44,0x3e8ebeed,
0xbec63f00,0x3ea20000,0xbeff3eb5,0xbd493eb5,0x3e713dc8,0x3ee2befb,0xbe153ed5,0x3ef5be8e,0x3ef5beed,0xbe15be44,0x3ee2be44,0x3e71beed,0xbd49be8e,0xbeff3ed5,0x3ea2befb,0xbec63dc8,
0xbeb53f00,0xbeb50000,0xbeb53f00,0xbeb50000,0x3eb50000,0xbeb53f00,0x3eb50000,0xbeb53f00,0x3eb5bf00,0x3eb50000,0x3eb5bf00,0x3eb50000,0xbeb50000,0x3eb5bf00,0xbeb50000,0x3eb5bf00,
0x3d493f00,0x3eff0000,0x3ec63eb5,0x3ea2beb5,0xbe15befb,0xbef53dc8,0xbee2be8e,0xbe713ed5,0x3e713eed,0x3ee2be44,0x3ef53e44,0x3e15beed,0xbea2bed5,0xbec63e8e,0xbeffbdc8,0xbd493efb,
0x3dc83f00,0x3efb0000,0x3efb0000,0xbdc8bf00,0xbe8ebeed,0xbed53e44,0xbed53e44,0x3e8e3eed,0x3ed53eb5,0x3e8ebeb5,0x3e8ebeb5,0xbed5beb5,0xbefbbe44,0xbdc83eed,0xbdc83eed,0x3efb3e44,
0x3e153f00,0x3ef50000,0x3e71beb5,0xbee2beb5,0xbec6bed5,0xbea23e8e,0x3d493efb,0x3eff3dc8,0x3eff3e44,0x3d49beed,0xbea2beed,0xbec63e44,0xbee23dc8,0x3e713efb,0x3ef53e8e,0x3e15bed5,
0x3e443f00,0x3eed0000,0xbe44bf00,0xbeed0000,0xbeedbeb5,0xbe443eb5,0x3eed3eb5,0x3e44beb5,0x3eed0000,0xbe44bf00,0xbeed0000,0x3e443f00,0xbe443eb5,0x3eed3eb5,0x3e44beb5,0xbeedbeb5,
0x3e713f00,0x3ee20000,0xbef5beb5,0xbe153eb5,0xbeffbe8e,0xbd493ed5,0x3ec6bdc8,0xbea2befb,0x3ea2be44,0xbec6beed,0x3d493eed,0x3eff3e44,0x3e153efb,0x3ef53dc8,0xbee2bed5,0xbe713e8e,
0x3e8e3f00,0x3ed50000,0xbed50000,0x3e8e3f00,0xbefbbe44,0x3dc83eed,0xbdc8beed,0xbefbbe44,0x3dc8beb5,0xbefbbeb5,0x3efb3eb5,0x3dc8beb5,0x3ed53eed,0x3e8ebe44,0xbe8e3e44,0x3ed53eed,
0x3ea23f00,0x3ec60000,0xbd493eb5,0x3eff3eb5,0xbee2bdc8,0x3e713efb,0xbef5bed5,0xbe153e8e,0xbe15beed,0xbef5be44,0x3e71be44,0xbee2beed,0x3eff3e8e,0xbd49bed5,0x3ec63efb,0x3ea2bdc8,
0x3f003f00,0xbf003f00,0x3f003f00,0xbf003f00,0x3f003f00,0xbf003f00,0x3f003f00,0xbf003f00,0x3f003f00,0xbf003f00,0x3f003f00,0xbf003f00,0x3f003f00,0xbf003f00,0x3f003f00,0xbf003f00,
0xbd490000,0xbeffbf00,0xbec6beb5,0xbea2beb5,0xbe15bdc8,0xbef5befb,0xbee2bed5,0xbe71be8e,0xbe71be44,0xbee2beed,0xbef5beed,0xbe15be44,0xbea2be8e,0xbec6bed5,0xbeffbefb,0xbd49bdc8,
0xbefbbf00,0x3dc80000,0x3dc80000,0x3efb3f00,0xbed5beed,0x3e8e3e44,0x3e8e3e44,0x3ed53eed,0xbe8ebeb5,0x3ed53eb5,0x3ed53eb5,0x3e8e3eb5,0xbdc8be44,0x3efb3eed,0x3efb3eed,0x3dc83e44,
0x3e150000,0x3ef53f00,0x3e713eb5,0xbee2beb5,0x3ec63e8e,0x3ea23ed5,0xbd493dc8,0xbeffbefb,0x3eff3eed,0x3d493e44,0xbea2be44,0xbec6beed,0x3ee23efb,0xbe71bdc8,0xbef5bed5,0xbe15be8e,
0x3eed3f00,0xbe440000,0xbeedbf00,0x3e440000,0x3e443eb5,0xbeedbeb5,0xbe44beb5,0x3eed3eb5,0xbe440000,0xbeedbf00,0x3e440000,0x3eed3f00,0xbeedbeb5,0xbe44beb5,0x3eed3eb5,0x3e443eb5,
0xbe710000,0xbee2bf00,0x3ef53eb5,0x3e153eb5,0xbeffbed5,0xbd49be8e,0x3ec63efb,0xbea2bdc8,0xbea2beed,0x3ec63e44,0xbd493e44,0xbeffbeed,0x3e15bdc8,0x3ef53efb,0xbee2be8e,0xbe71bed5,
0xbed5bf00,0x3e8e0000,0xbe8e0000,0xbed5bf00,0x3dc8be44,0x3efb3eed,0xbefbbeed,0x3dc8be44,0x3efb3eb5,0x3dc83eb5,0xbdc8beb5,0x3efb3eb5,0x3e8e3eed,0xbed5be44,0x3ed53e44,0x3e8e3eed,
0x3ea20000,0x3ec63f00,0xbd49beb5,0x3eff3eb5,0x3ee23efb,0xbe713dc8,0x3ef53e8e,0x3e153ed5,0xbe153e44,0xbef5beed,0x3e713eed,0xbee2be44,0xbeffbed5,0x3d49be8e,0xbec6bdc8,0xbea2befb,
0x3f00,0xbf000000,0x3f00,0xbf000000,0xbf00,0x3f000000,0xbf00,0x3f000000,0x3f00,0xbf000000,0x3f00,0xbf000000,0xbf00,0x3f000000,0xbf00,0x3f000000,
0xbeff0000,0x3d49bf00,0xbea2beb5,0x3ec6beb5,0x3ef53dc8,0xbe153efb,0x3e713ed5,0xbee23e8e,0xbee2be44,0x3e71beed,0xbe15beed,0x3ef5be44,0x3ec63e8e,0xbea23ed5,0x3d493efb,0xbeff3dc8,
0x3dc8bf00,0x3efb0000,0x3efb0000,0xbdc83f00,0xbe8e3eed,0xbed5be44,0xbed5be44,0x3e8ebeed,0x3ed5beb5,0x3e8e3eb5,0x3e8e3eb5,0xbed53eb5,0xbefb3e44,0xbdc8beed,0xbdc8beed,0x3efbbe44,
0x3ef50000,0xbe153f00,0xbee23eb5,0xbe71beb5,0xbea2be8e,0x3ec6bed5,0x3effbdc8,0xbd493efb,0x3d493eed,0xbeff3e44,0xbec6be44,0x3ea2beed,0x3e71befb,0x3ee23dc8,0x3e153ed5,0xbef53e8e,
0xbe443f00,0xbeed0000,0x3e44bf00,0x3eed0000,0x3eedbeb5,0x3e443eb5,0xbeed3eb5,0xbe44beb5,0xbeed0000,0x3e44bf00,0x3eed0000,0xbe443f00,0x3e443eb5,0xbeed3eb5,0xbe44beb5,0x3eedbeb5,
0xbee20000,0x3e71bf00,0x3e153eb5,0xbef53eb5,0x3d493ed5,0xbeff3e8e,0x3ea2befb,0x3ec63dc8,0x3ec6beed,0x3ea23e44,0xbeff3e44,0x3d49beed,0xbef53dc8,0x3e15befb,0x3e713e8e,0xbee23ed5,
0x3e8ebf00,0x3ed50000,0xbed50000,0x3e8ebf00,0xbefb3e44,0x3dc8beed,0xbdc83eed,0xbefb3e44,0x3dc83eb5,0xbefb3eb5,0x3efbbeb5,0x3dc83eb5,0x3ed5beed,0x3e8e3e44,0xbe8ebe44,0x3ed5beed,
0x3ec60000,0xbea23f00,0x3effbeb5,0x3d493eb5,0x3e71befb,0x3ee2bdc8,0xbe15be8e,0x3ef5bed5,0xbef53e44,0x3e15beed,0xbee23eed,0xbe71be44,0xbd493ed5,0xbeff3e8e,0x3ea23dc8,0xbec63efb,
0x3eb53f00,0xbeb50000,0x3eb53f00,0xbeb50000,0xbeb50000,0xbeb5bf00,0xbeb50000,0xbeb5bf00,0xbeb5bf00,0x3eb50000,0xbeb5bf00,0x3eb50000,0x3eb50000,0x3eb53f00,0x3eb50000,0x3eb53f00,
0x3d490000,0x3effbf00,0x3ec6beb5,0x3ea2beb5,0x3e15bdc8,0x3ef5befb,0x3ee2bed5,0x3e71be8e,0x3e71be44,0x3ee2beed,0x3ef5beed,0x3e15be44,0x3ea2be8e,0x3ec6bed5,0x3effbefb,0x3d49bdc8,
0x3efbbf00,0xbdc80000,0xbdc80000,0xbefb3f00,0x3ed5beed,0xbe8e3e44,0xbe8e3e44,0xbed53eed,0x3e8ebeb5,0xbed53eb5,0xbed53eb5,0xbe8e3eb5,0x3dc8be44,0xbefb3eed,0xbefb3eed,0xbdc83e44,
0xbe150000,0xbef53f00,0xbe713eb5,0x3ee2beb5,0xbec63e8e,0xbea23ed5,0x3d493dc8,0x3effbefb,0xbeff3eed,0xbd493e44,0x3ea2be44,0x3ec6beed,0xbee23efb,0x3e71bdc8,0x3ef5bed5,0x3e15be8e,
0xbeed3f00,0x3e440000,0x3eedbf00,0xbe440000,0xbe443eb5,0x3eedbeb5,0x3e44beb5,0xbeed3eb5,0x3e440000,0x3eedbf00,0xbe440000,0xbeed3f00,0x3eedbeb5,0x3e44beb5,0xbeed3eb5,0xbe443eb5,
0x3e710000,0x3ee2bf00,0xbef53eb5,0xbe153eb5,0x3effbed5,0x3d49be8e,0xbec63efb,0x3ea2bdc8,0x3ea2beed,0xbec63e44,0x3d493e44,0x3effbeed,0xbe15bdc8,0xbef53efb,0x3ee2be8e,0x3e71bed5,
0x3ed5bf00,0xbe8e0000,0x3e8e0000,0x3ed5bf00,0xbdc8be44,0xbefb3eed,0x3efbbeed,0xbdc8be44,0xbefb3eb5,0xbdc83eb5,0x3dc8beb5,0xbefb3eb5,0xbe8e3eed,0x3ed5be44,0xbed53e44,0xbe8e3eed,
0xbea20000,0xbec63f00,0x3d49beb5,0xbeff3eb5,0xbee23efb,0x3e713dc8,0xbef53e8e,0xbe153ed5,0x3e153e44,0x3ef5beed,0xbe713eed,0x3ee2be44,0x3effbed5,0xbd49be8e,0x3ec6bdc8,0x3ea2befb,
0xbeb53f00,0xbeb50000,0xbeb53f00,0xbeb50000,0x3eb50000,0xbeb53f00,0x3eb50000,0xbeb53f00,0x3eb5bf00,0x3eb50000,0x3eb5bf00,0x3eb50000,0xbeb50000,0x3eb5bf00,0xbeb50000,0x3eb5bf00,
0x3eff0000,0xbd49bf00,0x3ea2beb5,0xbec6beb5,0xbef53dc8,0x3e153efb,0xbe713ed5,0x3ee23e8e,0x3ee2be44,0xbe71beed,0x3e15beed,0xbef5be44,0xbec63e8e,0x3ea23ed5,0xbd493efb,0x3eff3dc8,
0xbdc8bf00,0xbefb0000,0xbefb0000,0x3dc83f00,0x3e8e3eed,0x3ed5be44,0x3ed5be44,0xbe8ebeed,0xbed5beb5,0xbe8e3eb5,0xbe8e3eb5,0x3ed53eb5,0x3efb3e44,0x3dc8beed,0x3dc8beed,0xbefbbe44,
0xbef50000,0x3e153f00,0x3ee23eb5,0x3e71beb5,0x3ea2be8e,0xbec6bed5,0xbeffbdc8,0x3d493efb,0xbd493eed,0x3eff3e44,0x3ec6be44,0xbea2beed,0xbe71befb,0xbee23dc8,0xbe153ed5,0x3ef53e8e,
0x3e443f00,0x3eed0000,0xbe44bf00,0xbeed0000,0xbeedbeb5,0xbe443eb5,0x3eed3eb5,0x3e44beb5,0x3eed0000,0xbe44bf00,0xbeed0000,0x3e443f00,0xbe443eb5,0x3eed3eb5,0x3e44beb5,0xbeedbeb5,
0x3ee20000,0xbe71bf00,0xbe153eb5,0x3ef53eb5,0xbd493ed5,0x3eff3e8e,0xbea2befb,0xbec63dc8,0xbec6beed,0xbea23e44,0x3eff3e44,0xbd49beed,0x3ef53dc8,0xbe15befb,0xbe713e8e,0x3ee23ed5,
0xbe8ebf00,0xbed50000,0x3ed50000,0xbe8ebf00,0x3efb3e44,0xbdc8beed,0x3dc83eed,0x3efb3e44,0xbdc83eb5,0x3efb3eb5,0xbefbbeb5,0xbdc83eb5,0xbed5beed,0xbe8e3e44,0x3e8ebe44,0xbed5beed,
0xbec60000,0x3ea23f00,0xbeffbeb5,0xbd493eb5,0xbe71befb,0xbee2bdc8,0x3e15be8e,0xbef5bed5,0x3ef53e44,0xbe15beed,0x3ee23eed,0x3e71be44,0x3d493ed5,0x3eff3e8e,0xbea23dc8,0x3ec63efb,
0x3f003f00,0xbf003f00,0x3f003f00,0xbf003f00,0x3f003f00,0xbf003f00,0x3f003f00,0xbf003f00,0x3f003f00,0xbf003f00,0x3f003f00,0xbf003f00,0x3f003f00,0xbf003f00,0x3f003f00,0xbf003f00,
0xbeffbf00,0x3d490000,0xbea2beb5,0x3ec63eb5,0xbef5befb,0x3e153dc8,0xbe71be8e,0x3ee23ed5,0xbee2beed,0x3e713e44,0xbe15be44,0x3ef53eed,0xbec6bed5,0x3ea23e8e,0xbd49bdc8,0x3eff3efb,
0x3efb3f00,0xbdc80000,0xbdc80000,0xbefbbf00,0x3ed53eed,0xbe8ebe44,0xbe8ebe44,0xbed5beed,0x3e8e3eb5,0xbed5beb5,0xbed5beb5,0xbe8ebeb5,0x3dc83e44,0xbefbbeed,0xbefbbeed,0xbdc8be44,
0xbef5bf00,0x3e150000,0x3ee23eb5,0x3e713eb5,0xbea2bed5,0x3ec63e8e,0x3eff3efb,0xbd493dc8,0xbd49be44,0x3eff3eed,0x3ec63eed,0xbea2be44,0x3e713dc8,0x3ee23efb,0x3e153e8e,0xbef5bed5,
0x3eed3f00,0xbe440000,0xbeedbf00,0x3e440000,0x3e443eb5,0xbeedbeb5,0xbe44beb5,0x3eed3eb5,0xbe440000,0xbeedbf00,0x3e440000,0x3eed3f00,0xbeedbeb5,0xbe44beb5,0x3eed3eb5,0x3e443eb5,
0xbee2bf00,0x3e710000,0x3e153eb5,0xbef5beb5,0xbd49be8e,0x3eff3ed5,0xbea2bdc8,0xbec6befb,0x3ec63e44,0x3ea23eed,0xbeffbeed,0x3d49be44,0x3ef53efb,0xbe153dc8,0xbe71bed5,0x3ee23e8e,
0x3ed53f00,0xbe8e0000,0x3e8e0000,0x3ed53f00,0xbdc83e44,0xbefbbeed,0x3efb3eed,0xbdc83e44,0xbefbbeb5,0xbdc8beb5,0x3dc83eb5,0xbefbbeb5,0xbe8ebeed,0x3ed53e44,0xbed5be44,0xbe8ebeed,
0xbec6bf00,0x3ea20000,0xbeffbeb5,0xbd49beb5,0x3e71bdc8,0x3ee23efb,0xbe15bed5,0x3ef53e8e,0x3ef53eed,0xbe153e44,0x3ee23e44,0x3e713eed,0xbd493e8e,0xbeffbed5,0x3ea23efb,0xbec6bdc8,
0x3f00,0xbf000000,0x3f00,0xbf000000,0xbf00,0x3f000000,0xbf00,0x3f000000,0x3f00,0xbf000000,0x3f00,0xbf000000,0xbf00,0x3f000000,0xbf00,0x3f000000,
0x3d49bf00,0x3eff0000,0x3ec6beb5,0x3ea23eb5,0xbe153efb,0xbef5bdc8,0xbee23e8e,0xbe71bed5,0x3e71beed,0x3ee23e44,0x3ef5be44,0x3e153eed,0xbea23ed5,0xbec6be8e,0xbeff3dc8,0xbd49befb,
0xbdc83f00,0xbefb0000,0xbefb0000,0x3dc8bf00,0x3e8ebeed,0x3ed53e44,0x3ed53e44,0xbe8e3eed,0xbed53eb5,0xbe8ebeb5,0xbe8ebeb5,0x3ed5beb5,0x3efbbe44,0x3dc83eed,0x3dc83eed,0xbefb3e44,
0x3e15bf00,0x3ef50000,0x3e713eb5,0xbee23eb5,0xbec63ed5,0xbea2be8e,0x3d49befb,0x3effbdc8,0x3effbe44,0x3d493eed,0xbea23eed,0xbec6be44,0xbee2bdc8,0x3e71befb,0x3ef5be8e,0x3e153ed5,
0xbe443f00,0xbeed0000,0x3e44bf00,0x3eed0000,0x3eedbeb5,0x3e443eb5,0xbeed3eb5,0xbe44beb5,0xbeed0000,0x3e44bf00,0x3eed0000,0xbe443f00,0x3e443eb5,0xbeed3eb5,0xbe44beb5,0x3eedbeb5,
0x3e71bf00,0x3ee20000,0xbef53eb5,0xbe15beb5,0xbeff3e8e,0xbd49bed5,0x3ec63dc8,0xbea23efb,0x3ea23e44,0xbec63eed,0x3d49beed,0x3effbe44,0x3e15befb,0x3ef5bdc8,0xbee23ed5,0xbe71be8e,
0xbe8e3f00,0xbed50000,0x3ed50000,0xbe8e3f00,0x3efbbe44,0xbdc83eed,0x3dc8beed,0x3efbbe44,0xbdc8beb5,0x3efbbeb5,0xbefb3eb5,0xbdc8beb5,0xbed53eed,0xbe8ebe44,0x3e8e3e44,0xbed53eed,
0x3ea2bf00,0x3ec60000,0xbd49beb5,0x3effbeb5,0xbee23dc8,0x3e71befb,0xbef53ed5,0xbe15be8e,0xbe153eed,0xbef53e44,0x3e713e44,0xbee23eed,0x3effbe8e,0xbd493ed5,0x3ec6befb,0x3ea23dc8,
0x3eb53f00,0xbeb50000,0x3eb53f00,0xbeb50000,0xbeb50000,0xbeb5bf00,0xbeb50000,0xbeb5bf00,0xbeb5bf00,0x3eb50000,0xbeb5bf00,0x3eb50000,0x3eb50000,0x3eb53f00,0x3eb50000,0x3eb53f00,
0x3effbf00,0xbd490000,0x3ea2beb5,0xbec63eb5,0x3ef5befb,0xbe153dc8,0x3e71be8e,0xbee23ed5,0x3ee2beed,0xbe713e44,0x3e15be44,0xbef53eed,0x3ec6bed5,0xbea23e8e,0x3d49bdc8,0xbeff3efb,
0xbefb3f00,0x3dc80000,0x3dc80000,0x3efbbf00,0xbed53eed,0x3e8ebe44,0x3e8ebe44,0x3ed5beed,0xbe8e3eb5,0x3ed5beb5,0x3ed5beb5,0x3e8ebeb5,0xbdc83e44,0x3efbbeed,0x3efbbeed,0x3dc8be44,
0x3ef5bf00,0xbe150000,0xbee23eb5,0xbe713eb5,0x3ea2bed5,0xbec63e8e,0xbeff3efb,0x3d493dc8,0x3d49be44,0xbeff3eed,0xbec63eed,0x3ea2be44,0xbe713dc8,0xbee23efb,0xbe153e8e,0x3ef5bed5,
0xbeed3f00,0x3e440000,0x3eedbf00,0xbe440000,0xbe443eb5,0x3eedbeb5,0x3e44beb5,0xbeed3eb5,0x3e440000,0x3eedbf00,0xbe440000,0xbeed3f00,0x3eedbeb5,0x3e44beb5,0xbeed3eb5,0xbe443eb5,
0x3ee2bf00,0xbe710000,0xbe153eb5,0x3ef5beb5,0x3d49be8e,0xbeff3ed5,0x3ea2bdc8,0x3ec6befb,0xbec63e44,0xbea23eed,0x3effbeed,0xbd49be44,0xbef53efb,0x3e153dc8,0x3e71bed5,0xbee23e8e,
0xbed53f00,0x3e8e0000,0xbe8e0000,0xbed53f00,0x3dc83e44,0x3efbbeed,0xbefb3eed,0x3dc83e44,0x3efbbeb5,0x3dc8beb5,0xbdc83eb5,0x3efbbeb5,0x3e8ebeed,0xbed53e44,0x3ed5be44,0x3e8ebeed,
0x3ec6bf00,0xbea20000,0x3effbeb5,0x3d49beb5,0xbe71bdc8,0xbee23efb,0x3e15bed5,0xbef53e8e,0xbef53eed,0x3e153e44,0xbee23e44,0xbe713eed,0x3d493e8e,0x3effbed5,0xbea23efb,0x3ec6bdc8,
0xbeb53f00,0xbeb50000,0xbeb53f00,0xbeb50000,0x3eb50000,0xbeb53f00,0x3eb50000,0xbeb53f00,0x3eb5bf00,0x3eb50000,0x3eb5bf00,0x3eb50000,0xbeb50000,0x3eb5bf00,0xbeb50000,0x3eb5bf00,
0xbd49bf00,0xbeff0000,0xbec6beb5,0xbea23eb5,0x3e153efb,0x3ef5bdc8,0x3ee23e8e,0x3e71bed5,0xbe71beed,0xbee23e44,0xbef5be44,0xbe153eed,0x3ea23ed5,0x3ec6be8e,0x3eff3dc8,0x3d49befb,
0x3dc83f00,0x3efb0000,0x3efb0000,0xbdc8bf00,0xbe8ebeed,0xbed53e44,0xbed53e44,0x3e8e3eed,0x3ed53eb5,0x3e8ebeb5,0x3e8ebeb5,0xbed5beb5,0xbefbbe44,0xbdc83eed,0xbdc83eed,0x3efb3e44,
0xbe15bf00,0xbef50000,0xbe713eb5,0x3ee23eb5,0x3ec63ed5,0x3ea2be8e,0xbd49befb,0xbeffbdc8,0xbeffbe44,0xbd493eed,0x3ea23eed,0x3ec6be44,0x3ee2bdc8,0xbe71befb,0xbef5be8e,0xbe153ed5,
0x3e443f00,0x3eed0000,0xbe44bf00,0xbeed0000,0xbeedbeb5,0xbe443eb5,0x3eed3eb5,0x3e44beb5,0x3eed0000,0xbe44bf00,0xbeed0000,0x3e443f00,0xbe443eb5,0x3eed3eb5,0x3e44beb5,0xbeedbeb5,
0xbe71bf00,0xbee20000,0x3ef53eb5,0x3e15beb5,0x3eff3e8e,0x3d49bed5,0xbec63dc8,0x3ea23efb,0xbea23e44,0x3ec63eed,0xbd49beed,0xbeffbe44,0xbe15befb,0xbef5bdc8,0x3ee23ed5,0x3e71be8e,
0x3e8e3f00,0x3ed50000,0xbed50000,0x3e8e3f00,0xbefbbe44,0x3dc83eed,0xbdc8beed,0xbefbbe44,0x3dc8beb5,0xbefbbeb5,0x3efb3eb5,0x3dc8beb5,0x3ed53eed,0x3e8ebe44,0xbe8e3e44,0x3ed53eed,
0xbea2bf00,0xbec60000,0x3d49beb5,0xbeffbeb5,0x3ee23dc8,0xbe71befb,0x3ef53ed5,0x3e15be8e,0x3e153eed,0x3ef53e44,0xbe713e44,0x3ee23eed,0xbeffbe8e,0x3d493ed5,0xbec6befb,0xbea23dc8,
0x3f003f00,0xbf003f00,0x3f003f00,0xbf003f00,0x3f003f00,0xbf003f00,0x3f003f00,0xbf003f00,0x3f003f00,0xbf003f00,0x3f003f00,0xbf003f00,0x3f003f00,0xbf003f00,0x3f003f00,0xbf003f00,
0x3d490000,0x3eff3f00,0x3ec63eb5,0x3ea23eb5,0x3e153dc8,0x3ef53efb,0x3ee23ed5,0x3e713e8e,0x3e713e44,0x3ee23eed,0x3ef53eed,0x3e153e44,0x3ea23e8e,0x3ec63ed5,0x3eff3efb,0x3d493dc8,
0xbefbbf00,0x3dc80000,0x3dc80000,0x3efb3f00,0xbed5beed,0x3e8e3e44,0x3e8e3e44,0x3ed53eed,0xbe8ebeb5,0x3ed53eb5,0x3ed53eb5,0x3e8e3eb5,0xbdc8be44,0x3efb3eed,0x3efb3eed,0x3dc83e44,
0xbe150000,0xbef5bf00,0xbe71beb5,0x3ee23eb5,0xbec6be8e,0xbea2bed5,0x3d49bdc8,0x3eff3efb,0xbeffbeed,0xbd49be44,0x3ea23e44,0x3ec63eed,0xbee2befb,0x3e713dc8,0x3ef53ed5,0x3e153e8e,
0x3eed3f00,0xbe440000,0xbeedbf00,0x3e440000,0x3e443eb5,0xbeedbeb5,0xbe44beb5,0x3eed3eb5,0xbe440000,0xbeedbf00,0x3e440000,0x3eed3f00,0xbeedbeb5,0xbe44beb5,0x3eed3eb5,0x3e443eb5,
0x3e710000,0x3ee23f00,0xbef5beb5,0xbe15beb5,0x3eff3ed5,0x3d493e8e,0xbec6befb,0x3ea23dc8,0x3ea23eed,0xbec6be44,0x3d49be44,0x3eff3eed,0xbe153dc8,0xbef5befb,0x3ee23e8e,0x3e713ed5,
0xbed5bf00,0x3e8e0000,0xbe8e0000,0xbed5bf00,0x3dc8be44,0x3efb3eed,0xbefbbeed,0x3dc8be44,0x3efb3eb5,0x3dc83eb5,0xbdc8beb5,0x3efb3eb5,0x3e8e3eed,0xbed5be44,0x3ed53e44,0x3e8e3eed,
0xbea20000,0xbec6bf00,0x3d493eb5,0xbeffbeb5,0xbee2befb,0x3e71bdc8,0xbef5be8e,0xbe15bed5,0x3e15be44,0x3ef53eed,0xbe71beed,0x3ee23e44,0x3eff3ed5,0xbd493e8e,0x3ec63dc8,0x3ea23efb,
0x3f00,0xbf000000,0x3f00,0xbf000000,0xbf00,0x3f000000,0xbf00,0x3f000000,0x3f00,0xbf000000,0x3f00,0xbf000000,0xbf00,0x3f000000,0xbf00,0x3f000000,
0x3eff0000,0xbd493f00,0x3ea23eb5,0xbec63eb5,0xbef5bdc8,0x3e15befb,0xbe71bed5,0x3ee2be8e,0x3ee23e44,0xbe713eed,0x3e153eed,0xbef53e44,0xbec6be8e,0x3ea2bed5,0xbd49befb,0x3effbdc8,
0x3dc8bf00,0x3efb0000,0x3efb0000,0xbdc83f00,0xbe8e3eed,0xbed5be44,0xbed5be44,0x3e8ebeed,0x3ed5beb5,0x3e8e3eb5,0x3e8e3eb5,0xbed53eb5,0xbefb3e44,0xbdc8beed,0xbdc8beed,0x3efbbe44,
0xbef50000,0x3e15bf00,0x3ee2beb5,0x3e713eb5,0x3ea23e8e,0xbec63ed5,0xbeff3dc8,0x3d49befb,0xbd49beed,0x3effbe44,0x3ec63e44,0xbea23eed,0xbe713efb,0xbee2bdc8,0xbe15bed5,0x3ef5be8e,
0xbe443f00,0xbeed0000,0x3e44bf00,0x3eed0000,0x3eedbeb5,0x3e443eb5,0xbeed3eb5,0xbe44beb5,0xbeed0000,0x3e44bf00,0x3eed0000,0xbe443f00,0x3e443eb5,0xbeed3eb5,0xbe44beb5,0x3eedbeb5,
0x3ee20000,0xbe713f00,0xbe15beb5,0x3ef5beb5,0xbd49bed5,0x3effbe8e,0xbea23efb,0xbec6bdc8,0xbec63eed,0xbea2be44,0x3effbe44,0xbd493eed,0x3ef5bdc8,0xbe153efb,0xbe71be8e,0x3ee2bed5,
0x3e8ebf00,0x3ed50000,0xbed50000,0x3e8ebf00,0xbefb3e44,0x3dc8beed,0xbdc83eed,0xbefb3e44,0x3dc83eb5,0xbefb3eb5,0x3efbbeb5,0x3dc83eb5,0x3ed5beed,0x3e8e3e44,0xbe8ebe44,0x3ed5beed,
0xbec60000,0x3ea2bf00,0xbeff3eb5,0xbd49beb5,0xbe713efb,0xbee23dc8,0x3e153e8e,0xbef53ed5,0x3ef5be44,0xbe153eed,0x3ee2beed,0x3e713e44,0x3d49bed5,0x3effbe8e,0xbea2bdc8,0x3ec6befb,
0x3eb53f00,0xbeb50000,0x3eb53f00,0xbeb50000,0xbeb50000,0xbeb5bf00,0xbeb50000,0xbeb5bf00,0xbeb5bf00,0x3eb50000,0xbeb5bf00,0x3eb50000,0x3eb50000,0x3eb53f00,0x3eb50000,0x3eb53f00,
0xbd490000,0xbeff3f00,0xbec63eb5,0xbea23eb5,0xbe153dc8,0xbef53efb,0xbee23ed5,0xbe713e8e,0xbe713e44,0xbee23eed,0xbef53eed,0xbe153e44,0xbea23e8e,0xbec63ed5,0xbeff3efb,0xbd493dc8,
0x3efbbf00,0xbdc80000,0xbdc80000,0xbefb3f00,0x3ed5beed,0xbe8e3e44,0xbe8e3e44,0xbed53eed,0x3e8ebeb5,0xbed53eb5,0xbed53eb5,0xbe8e3eb5,0x3dc8be44,0xbefb3eed,0xbefb3eed,0xbdc83e44,
0x3e150000,0x3ef5bf00,0x3e71beb5,0xbee23eb5,0x3ec6be8e,0x3ea2bed5,0xbd49bdc8,0xbeff3efb,0x3effbeed,0x3d49be44,0xbea23e44,0xbec63eed,0x3ee2befb,0xbe713dc8,0xbef53ed5,0xbe153e8e,
0xbeed3f00,0x3e440000,0x3eedbf00,0xbe440000,0xbe443eb5,0x3eedbeb5,0x3e44beb5,0xbeed3eb5,0x3e440000,0x3eedbf00,0xbe440000,0xbeed3f00,0x3eedbeb5,0x3e44beb5,0xbeed3eb5,0xbe443eb5,
0xbe710000,0xbee23f00,0x3ef5beb5,0x3e15beb5,0xbeff3ed5,0xbd493e8e,0x3ec6befb,0xbea23dc8,0xbea23eed,0x3ec6be44,0xbd49be44,0xbeff3eed,0x3e153dc8,0x3ef5befb,0xbee23e8e,0xbe713ed5,
0x3ed5bf00,0xbe8e0000,0x3e8e0000,0x3ed5bf00,0xbdc8be44,0xbefb3eed,0x3efbbeed,0xbdc8be44,0xbefb3eb5,0xbdc83eb5,0x3dc8beb5,0xbefb3eb5,0xbe8e3eed,0x3ed5be44,0xbed53e44,0xbe8e3eed,
0x3ea20000,0x3ec6bf00,0xbd493eb5,0x3effbeb5,0x3ee2befb,0xbe71bdc8,0x3ef5be8e,0x3e15bed5,0xbe15be44,0xbef53eed,0x3e71beed,0xbee23e44,0xbeff3ed5,0x3d493e8e,0xbec63dc8,0xbea23efb,
0xbeb53f00,0xbeb50000,0xbeb53f00,0xbeb50000,0x3eb50000,0xbeb53f00,0x3eb50000,0xbeb53f00,0x3eb5bf00,0x3eb50000,0x3eb5bf00,0x3eb50000,0xbeb50000,0x3eb5bf00,0xbeb50000,0x3eb5bf00,
0xbeff0000,0x3d493f00,0xbea23eb5,0x3ec63eb5,0x3ef5bdc8,0xbe15befb,0x3e71bed5,0xbee2be8e,0xbee23e44,0x3e713eed,0xbe153eed,0x3ef53e44,0x3ec6be8e,0xbea2bed5,0x3d49befb,0xbeffbdc8,
0xbdc8bf00,0xbefb0000,0xbefb0000,0x3dc83f00,0x3e8e3eed,0x3ed5be44,0x3ed5be44,0xbe8ebeed,0xbed5beb5,0xbe8e3eb5,0xbe8e3eb5,0x3ed53eb5,0x3efb3e44,0x3dc8beed,0x3dc8beed,0xbefbbe44,
0x3ef50000,0xbe15bf00,0xbee2beb5,0xbe713eb5,0xbea23e8e,0x3ec63ed5,0x3eff3dc8,0xbd49befb,0x3d49beed,0xbeffbe44,0xbec63e44,0x3ea23eed,0x3e713efb,0x3ee2bdc8,0x3e15bed5,0xbef5be8e,
0x3e443f00,0x3eed0000,0xbe44bf00,0xbeed0000,0xbeedbeb5,0xbe443eb5,0x3eed3eb5,0x3e44beb5,0x3eed0000,0xbe44bf00,0xbeed0000,0x3e443f00,0xbe443eb5,0x3eed3eb5,0x3e44beb5,0xbeedbeb5,
0xbee20000,0x3e713f00,0x3e15beb5,0xbef5beb5,0x3d49bed5,0xbeffbe8e,0x3ea23efb,0x3ec6bdc8,0x3ec63eed,0x3ea2be44,0xbeffbe44,0x3d493eed,0xbef5bdc8,0x3e153efb,0x3e71be8e,0xbee2bed5,
0xbe8ebf00,0xbed50000,0x3ed50000,0xbe8ebf00,0x3efb3e44,0xbdc8beed,0x3dc83eed,0x3efb3e44,0xbdc83eb5,0x3efb3eb5,0xbefbbeb5,0xbdc83eb5,0xbed5beed,0xbe8e3e44,0x3e8ebe44,0xbed5beed,
0x3ec60000,0xbea2bf00,0x3eff3eb5,0x3d49beb5,0x3e713efb,0x3ee23dc8,0xbe153e8e,0x3ef53ed5,0xbef5be44,0x3e153eed,0xbee2beed,0xbe713e44,0xbd49bed5,0xbeffbe8e,0x3ea2bdc8,0xbec6befb,
0x3f800000,0x0,0x3f800000,0x0,0x3f800000,0x0,0x3f800000,0x0,0x3f800000,0x0,0x3f800000,0x0,0x3f800000,0x0,0x3f800000,0x0,
0x3f800000,0x0,0x3f7fec43,0xbcc90ab0,0x3f7fb10f,0xbd48fb30,0x3f7f4e6d,0xbd96a905,0x3f7ec46d,0xbdc8bd36,0x3f7e1324,0xbdfab273,0x3f7d3aac,0xbe164083,0x3f7c3b28,0xbe2f10a2,
0x3f800000,0x0,0x3f7ffec4,0xbbc90f88,0x3f7ffb11,0xbc490e90,0x3f7ff4e6,0xbc96c9b6,0x3f7fec43,0xbcc90ab0,0x3f7fe129,0xbcfb49ba,0x3f7fd397,0xbd16c32c,0x3f7fc38f,0xbd2fe007,
0x3f800000,0x0,0x3f7fe129,0xbcfb49ba,0x3f7f84ab,0xbd7b2b74,0x3f7eea9d,0xbdbc3ac3,0x3f7e1324,0xbdfab273,0x3f7cfe73,0xbe1c76de,0x3f7baccd,0xbe3b6ecf,0x3f7a1e84,0xbe5a3997,
0x3f800000,0x0,0x3f7ffb11,0xbc490e90,0x3f7fec43,0xbcc90ab0,0x3f7fd397,0xbd16c32c,0x3f7fb10f,0xbd48fb30,0x3f7f84ab,0xbd7b2b74,0x3f7f4e6d,0xbd96a905,0x3f7f0e58,0xbdafb680,
0x3f800000,0x0,0x3f7fd397,0xbd16c32c,0x3f7f4e6d,0xbd96a905,0x3f7e70b0,0xbde1bc2e,0x3f7d3aac,0xbe164083,0x3f7baccd,0xbe3b6ecf,0x3f79c79d,0xbe605c13,0x3f778bc5,0xbe827dc0,
0x3f800000,0x0,0x3f7ff4e6,0xbc96c9b6,0x3f7fd397,0xbd16c32c,0x3f7f9c18,0xbd621469,0x3f7f4e6d,0xbd96a905,0x3f7eea9d,0xbdbc3ac3,0x3f7e70b0,0xbde1bc2e,0x3f7de0b1,0xbe039502,
0x3f800000,0x0,0x3f7fc38f,0xbd2fe007,0x3f7f0e58,0xbdafb680,0x3f7de0b1,0xbe039502,0x3f7c3b28,0xbe2f10a2,0x3f7a1e84,0xbe5a3997,0x3f778bc5,0xbe827dc0,0x3f748422,0xbe97a117,
0x3f800000,0x0,0x3f7fb10f,0xbd48fb30,0x3f7ec46d,0xbdc8bd36,0x3f7d3aac,0xbe164083,0x3f7b14be,0xbe47c5c2,0x3f7853f8,0xbe78cfcc,0x3f74fa0b,0xbe94a031,0x3f710908,0xbeac7cd4,
0x3f800000,0x0,0x3f7f4e6d,0xbd96a905,0x3f7d3aac,0xbe164083,0x3f79c79d,0xbe605c13,0x3f74fa0b,0xbe94a031,0x3f6ed89e,0xbeb8442a,0x3f676bd8,0xbedae880,0x3f5ebe05,0xbefc5d27,
0x3f800000,0x0,0x3f7f9c18,0xbd621469,0x3f7e70b0,0xbde1bc2e,0x3f7c7eb0,0xbe28defc,0x3f79c79d,0xbe605c13,0x3f764d97,0xbe8b9507,0x3f721352,0xbea68f12,0x3f6d1c1d,0xbec1071e,
0x3f800000,0x0,0x3f7f2f9d,0xbda3308c,0x3f7cbfc9,0xbe22abb6,0x3f78b47b,0xbe72b651,0x3f731447,0xbea09ae5,0x3f6be858,0xbec6d529,0x3f633c5a,0xbeebcbbb,0x3f591e6a,0xbf07a136,
0x3f800000,0x0,0x3f7f84ab,0xbd7b2b74,0x3f7e1324,0xbdfab273,0x3f7baccd,0xbe3b6ecf,0x3f7853f8,0xbe78cfcc,0x3f740bdd,0xbe9aa086,0x3f6ed89e,0xbeb8442a,0x3f68bf3c,0xbed53641,
0x3f800000,0x0,0x3f7f0e58,0xbdafb680,0x3f7c3b28,0xbe2f10a2,0x3f778bc5,0xbe827dc0,0x3f710908,0xbeac7cd4,0x3f68bf3c,0xbed53641,0x3f5ebe05,0xbefc5d27,0x3f531849,0xbf10d3cd,
0x3f800000,0x0,0x3f7f6ac7,0xbd8a200a,0x3f7dabcc,0xbe09cf86,0x3f7ac516,0xbe4dee60,0x3f76ba07,0xbe888e93,0x3f718f57,0xbea986c4,0x3f6b4b0c,0xbec9b953,0x3f63f473,0xbee900b7,
0x3f800000,0x0,0x3f7eea9d,0xbdbc3ac3,0x3f7baccd,0xbe3b6ecf,0x3f764d97,0xbe8b9507,0x3f6ed89e,0xbeb8442a,0x3f655e0b,0xbee363fa,0x3f59f26a,0xbf064b82,0x3f4cae79,0xbf19c200,
0x3f800000,0x0,0x3f7ec46d,0xbdc8bd36,0x3f7b14be,0xbe47c5c2,0x3f74fa0b,0xbe94a031,0x3f6c835e,0xbec3ef15,0x3f61c598,0xbef15aea,0x3f54db31,0xbf0e39da,0x3f45e403,0xbf226799,
0x3f800000,0x0,0x3f7e1324,0xbdfab273,0x3f7853f8,0xbe78cfcc,0x3f6ed89e,0xbeb8442a,0x3f61c598,0xbef15aea,0x3f514d3d,0xbf13682a,0x3f3daef9,0xbf2beb4a,0x3f273656,0xbf41d870,
0x3f800000,0x0,0x3f7e9bc9,0xbdd53db9,0x3f7a7302,0xbe541501,0x3f73913f,0xbe9d9e78,0x3f6a09a7,0xbecf7bca,0x3f5df6be,0xbeff17b2,0x3f4f7a1f,0xbf15f6d9,0x3f3ebc1b,0xbf2ac082,
0x3f800000,0x0,0x3f7de0b1,0xbe039502,0x3f778bc5,0xbe827dc0,0x3f6d1c1d,0xbec1071e,0x3f5ebe05,0xbefc5d27,0x3f4cae79,0xbf19c200,0x3f373a23,0xbf32c8c9,0x3f1ebc12,0xbf48d8b3,
0x3f800000,0x0,0x3f7e70b0,0xbde1bc2e,0x3f79c79d,0xbe605c13,0x3f721352,0xbea68f12,0x3f676bd8,0xbedae880,0x3f59f26a,0xbf064b82,0x3f49d112,0xbf1d7fd1,0x3f373a23,0xbf32c8c9,
0x3f800000,0x0,0x3f7dabcc,0xbe09cf86,0x3f76ba07,0xbe888e93,0x3f6b4b0c,0xbec9b953,0x3f5b941a,0xbf039c3d,0x3f47de65,0xbf1ff6cb,0x3f3085bb,0xbf396842,0x3f15f6d9,0xbf4f7a1f,
0x3f800000,0x0,0x3f7e4323,0xbdee3876,0x3f791298,0xbe6c9a7f,0x3f708066,0xbeaf713a,0x3f64aa59,0xbee63375,0x3f55b993,0xbf0cead0,0x3f43e200,0xbf24d225,0x3f2f61a5,0xbf3a7ca4,
0x3f800000,0x0,0x3f7d7474,0xbe1008b7,0x3f75dec6,0xbe8e9a22,0x3f696591,0xbed25a09,0x3f584853,0xbf08f59b,0x3f42de29,0xbf26050a,0x3f299415,0xbf3fc767,0x3f0cead0,0xbf55b993,
0x3f800000,0x0,0x3f7d3aac,0xbe164083,0x3f74fa0b,0xbe94a031,0x3f676bd8,0xbedae880,0x3f54db31,0xbf0e39da,0x3f3daef9,0xbf2beb4a,0x3f226799,0xbf45e403,0x3f039c3d,0xbf5b941a,
0x3f800000,0x0,0x3f7c3b28,0xbe2f10a2,0x3f710908,0xbeac7cd4,0x3f5ebe05,0xbefc5d27,0x3f45e403,0xbf226799,0x3f273656,0xbf41d870,0x3f039c3d,0xbf5b941a,0x3eb8442a,0xbf6ed89e,
0x3f800000,0x0,0x3f7cfe73,0xbe1c76de,0x3f740bdd,0xbe9aa086,0x3f655e0b,0xbee363fa,0x3f514d3d,0xbf13682a,0x3f385216,0xbf31a81d,0x3f1b02c6,0xbf4bbbf8,0x3ef41f07,0xbf6106f2,
0x3f800000,0x0,0x3f7bf531,0xbe354098,0x3f6ff573,0xbeb263ef,0x3f5c61c7,0xbf0242b1,0x3f41d870,0xbf273656,0x3f212ff9,0xbf46e22a,0x3ef6e0cb,0xbf604621,0x3ea395c5,0xbf7294f8,
0x3f800000,0x0,0x3f7cbfc9,0xbe22abb6,0x3f731447,0xbea09ae5,0x3f633c5a,0xbeebcbbb,0x3f4d9f02,0xbf187fc0,0x3f32c8c9,0xbf373a23,0x3f13682a,0xbf514d3d,0x3ee0924f,0xbf660f88,
0x3f800000,0x0,0x3f7baccd,0xbe3b6ecf,0x3f6ed89e,0xbeb8442a,0x3f59f26a,0xbf064b82,0x3f3daef9,0xbf2beb4a,0x3f1b02c6,0xbf4bbbf8,0x3ee63375,0xbf64aa59,0x3e8e9a22,0xbf75dec6,
0x3f800000,0x0,0x3f7c7eb0,0xbe28defc,0x3f721352,0xbea68f12,0x3f6106f2,0xbef41f07,0x3f49d112,0xbf1d7fd1,0x3f2d1469,0xbf3ca003,0x3f0b9a6b,0xbf5695e5,0x3ecc9b8b,0xbf6aab7b,
0x3f800000,0x0,0x3f7b61fc,0xbe419b37,0x3f6db293,0xbebe1d4a,0x3f577026,0xbf0a48ad,0x3f396842,0xbf3085bb,0x3f14b039,0xbf5064af,0x3ed53641,0xbf68bf3c,0x3e72b651,0xbf78b47b,
0x3f800000,0x0,0x3f800000,0x0,0x3f800000,0x0,0x3f800000,0x0,0x3f800000,0x0,0x3f800000,0x0,0x3f800000,0x0,0x3f800000,0x0,
0x3f7b14be,0xbe47c5c2,0x3f79c79d,0xbe605c13,0x3f7853f8,0xbe78cfcc,0x3f76ba07,0xbe888e93,0x3f74fa0b,0xbe94a031,0x3f731447,0xbea09ae5,0x3f710908,0xbeac7cd4,0x3f6ed89e,0xbeb8442a,
0x3f7fb10f,0xbd48fb30,0x3f7f9c18,0xbd621469,0x3f7f84ab,0xbd7b2b74,0x3f7f6ac7,0xbd8a200a,0x3f7f4e6d,0xbd96a905,0x3f7f2f9d,0xbda3308c,0x3f7f0e58,0xbdafb680,0x3f7eea9d,0xbdbc3ac3,
0x3f7853f8,0xbe78cfcc,0x3f764d97,0xbe8b9507,0x3f740bdd,0xbe9aa086,0x3f718f57,0xbea986c4,0x3f6ed89e,0xbeb8442a,0x3f6be858,0xbec6d529,0x3f68bf3c,0xbed53641,0x3f655e0b,0xbee363fa,
0x3f7ec46d,0xbdc8bd36,0x3f7e70b0,0xbde1bc2e,0x3f7e1324,0xbdfab273,0x3f7dabcc,0xbe09cf86,0x3f7d3aac,0xbe164083,0x3f7cbfc9,0xbe22abb6,0x3f7c3b28,0xbe2f10a2,0x3f7baccd,0xbe3b6ecf,
0x3f74fa0b,0xbe94a031,0x3f721352,0xbea68f12,0x3f6ed89e,0xbeb8442a,0x3f6b4b0c,0xbec9b953,0x3f676bd8,0xbedae880,0x3f633c5a,0xbeebcbbb,0x3f5ebe05,0xbefc5d27,0x3f59f26a,0xbf064b82,
0x3f7d3aac,0xbe164083,0x3f7c7eb0,0xbe28defc,0x3f7baccd,0xbe3b6ecf,0x3f7ac516,0xbe4dee60,0x3f79c79d,0xbe605c13,0x3f78b47b,0xbe72b651,0x3f778bc5,0xbe827dc0,0x3f764d97,0xbe8b9507,
0x3f710908,0xbeac7cd4,0x3f6d1c1d,0xbec1071e,0x3f68bf3c,0xbed53641,0x3f63f473,0xbee900b7,0x3f5ebe05,0xbefc5d27,0x3f591e6a,0xbf07a136,0x3f531849,0xbf10d3cd,0x3f4cae79,0xbf19c200,
0x3f6c835e,0xbec3ef15,0x3f676bd8,0xbedae880,0x3f61c598,0xbef15aea,0x3f5b941a,0xbf039c3d,0x3f54db31,0xbf0e39da,0x3f4d9f02,0xbf187fc0,0x3f45e403,0xbf226799,0x3f3daef9,0xbf2beb4a,
0x3f54db31,0xbf0e39da,0x3f49d112,0xbf1d7fd1,0x3f3daef9,0xbf2beb4a,0x3f3085bb,0xbf396842,0x3f226799,0xbf45e403,0x3f13682a,0xbf514d3d,0x3f039c3d,0xbf5b941a,0x3ee63375,0xbf64aa59,
0x3f676bd8,0xbedae880,0x3f6106f2,0xbef41f07,0x3f59f26a,0xbf064b82,0x3f5233c6,0xbf121eb0,0x3f49d112,0xbf1d7fd1,0x3f40d0da,0xbf286605,0x3f373a23,0xbf32c8c9,0x3f2d1469,0xbf3ca003,
0x3f4d9f02,0xbf187fc0,0x3f40d0da,0xbf286605,0x3f32c8c9,0xbf373a23,0x3f239da9,0xbf44e3f5,0x3f13682a,0xbf514d3d,0x3f0242b1,0xbf5c61c7,0x3ee0924f,0xbf660f88,0x3ebb31a0,0xbf6e46be,
0x3f61c598,0xbef15aea,0x3f59f26a,0xbf064b82,0x3f514d3d,0xbf13682a,0x3f47de65,0xbf1ff6cb,0x3f3daef9,0xbf2beb4a,0x3f32c8c9,0xbf373a23,0x3f273656,0xbf41d870,0x3f1b02c6,0xbf4bbbf8,
0x3f45e403,0xbf226799,0x3f373a23,0xbf32c8c9,0x3f273656,0xbf41d870,0x3f15f6d9,0xbf4f7a1f,0x3f039c3d,0xbf5b941a,0x3ee0924f,0xbf660f88,0x3eb8442a,0xbf6ed89e,0x3e8e9a22,0xbf75dec6,
0x3f5b941a,0xbf039c3d,0x3f5233c6,0xbf121eb0,0x3f47de65,0xbf1ff6cb,0x3f3ca003,0xbf2d1469,0x3f3085bb,0xbf396842,0x3f239da9,0xbf44e3f5,0x3f15f6d9,0xbf4f7a1f,0x3f07a136,0xbf591e6a,
0x3f3daef9,0xbf2beb4a,0x3f2d1469,0xbf3ca003,0x3f1b02c6,0xbf4bbbf8,0x3f07a136,0xbf591e6a,0x3ee63375,0xbf64aa59,0x3ebb31a0,0xbf6e46be,0x3e8e9a22,0xbf75dec6,0x3e419b37,0xbf7b61fc,
0x3f3504f3,0xbf3504f3,0x3f226799,0xbf45e403,0x3f0e39da,0xbf54db31,0x3ef15aea,0xbf61c598,0x3ec3ef15,0xbf6c835e,0x3e94a031,0xbf74fa0b,0x3e47c5c2,0xbf7b14be,0x3dc8bd36,0xbf7ec46d,
0x3f0e39da,0xbf54db31,0x3ee63375,0xbf64aa59,0x3eac7cd4,0xbf710908,0x3e605c13,0xbf79c79d,0x3dc8bd36,0xbf7ec46d,0xbcc90ab0,0xbf7fec43,0xbe164083,0xbf7d3aac,0xbe888e93,0xbf76ba07,
0x3f2beb4a,0xbf3daef9,0x3f173c07,0xbf4e8d90,0x3f00e7e4,0xbf5d2d53,0x3ed25a09,0xbf696591,0x3ea09ae5,0xbf731447,0x3e5a3997,0xbf7a1e84,0x3de1bc2e,0xbf7e70b0,0x3bc90f88,0xbf7ffec4,
0x3f039c3d,0xbf5b941a,0x3ecc9b8b,0xbf6aab7b,0x3e8e9a22,0xbf75dec6,0x3e1c76de,0xbf7cfe73,0x3cc90ab0,0xbf7fec43,0xbdd53db9,0xbf7e9bc9,0xbe6c9a7f,0xbf791298,0xbeb554ec,0xbf6f6830,
0x3f226799,0xbf45e403,0x3f0b9a6b,0xbf5695e5,0x3ee63375,0xbf64aa59,0x3eb263ef,0xbf6ff573,0x3e78cfcc,0xbf7853f8,0x3e09cf86,0xbf7dabcc,0x3cc90ab0,0xbf7fec43,0xbdafb680,0xbf7f0e58,
0x3ef15aea,0xbf61c598,0x3eb263ef,0xbf6ff573,0x3e605c13,0xbf79c79d,0x3dafb680,0xbf7f0e58,0xbd48fb30,0xbf7fb10f,0xbe3b6ecf,0xbf7baccd,0xbea09ae5,0xbf731447,0xbee0924f,0xbf660f88,
0x3f187fc0,0xbf4d9f02,0x3eff17b2,0xbf5df6be,0x3ec9b953,0xbf6b4b0c,0x3e919ddd,0xbf756d97,0x3e2f10a2,0xbf7c3b28,0x3d621469,0xbf7f9c18,0xbd7b2b74,0xbf7f84ab,0xbe354098,0xbf7bf531,
0x3edae880,0xbf676bd8,0x3e97a117,0xbf748422,0x3e22abb6,0xbf7cbfc9,0x3c96c9b6,0xbf7ff4e6,0xbdfab273,0xbf7e1324,0xbe8586ce,0xbf772417,0xbec9b953,0xbf6b4b0c,0xbf04f484,0xbf5ac450,
0x3ec3ef15,0xbf6c835e,0x3e78cfcc,0xbf7853f8,0x3dc8bd36,0xbf7ec46d,0xbd48fb30,0xbf7fb10f,0xbe47c5c2,0xbf7b14be,0xbeac7cd4,0xbf710908,0xbef15aea,0xbf61c598,0xbf187fc0,0xbf4d9f02,
0x3e47c5c2,0xbf7b14be,0x3cc90ab0,0xbf7fec43,0xbe164083,0xbf7d3aac,0xbea09ae5,0xbf731447,0xbef15aea,0xbf61c598,0xbf1d7fd1,0xbf49d112,0xbf3daef9,0xbf2beb4a,0xbf584853,0xbf08f59b,
0x3eac7cd4,0xbf710908,0x3e419b37,0xbf7b61fc,0x3d16c32c,0xbf7fd397,0xbdee3876,0xbf7e4323,0xbe888e93,0xbf76ba07,0xbed25a09,0xbf696591,0xbf0b9a6b,0xbf5695e5,0xbf2ac082,0xbf3ebc1b,
0x3e164083,0xbf7d3aac,0xbcfb49ba,0xbf7fe129,0xbe541501,0xbf7a7302,0xbec1071e,0xbf6d1c1d,0xbf08f59b,0xbf584853,0xbf2d1469,0xbf3ca003,0xbf4bbbf8,0xbf1b02c6,0xbf63f473,0xbee900b7,
0x3e94a031,0xbf74fa0b,0x3e09cf86,0xbf7dabcc,0xbcc90ab0,0xbf7fec43,0xbe3b6ecf,0xbf7baccd,0xbeac7cd4,0xbf710908,0xbef6e0cb,0xbf604621,0xbf1d7fd1,0xbf49d112,0xbf3b8f3b,0xbf2e3bde,
0x3dc8bd36,0xbf7ec46d,0xbdafb680,0xbf7f0e58,0xbe888e93,0xbf76ba07,0xbee0924f,0xbf660f88,0xbf187fc0,0xbf4d9f02,0xbf3b8f3b,0xbf2e3bde,0xbf584853,0xbf08f59b,0xbf6db293,0xbebe1d4a,
0x3e78cfcc,0xbf7853f8,0x3da3308c,0xbf7f2f9d,0xbdafb680,0xbf7f0e58,0xbe7ee6e1,0xbf77f110,0xbecf7bca,0xbf6a09a7,0xbf0cead0,0xbf55b993,0xbf2e3bde,0xbf3b8f3b,0xbf4ac77f,0xbf1c420c,
0x3d48fb30,0xbf7fb10f,0xbe1008b7,0xbf7d7474,0xbea68f12,0xbf721352,0xbeff17b2,0xbf5df6be,0xbf273656,0xbf41d870,0xbf48d8b3,0xbf1ebc12,0xbf633c5a,0xbeebcbbb,0xbf756d97,0xbe919ddd,
0x3f800000,0x0,0x3f800000,0x0,0x3f800000,0x0,0x3f800000,0x0,0x3f800000,0x0,0x3f800000,0x0,0x3f800000,0x0,0x3f800000,0x0,
0x3f6c835e,0xbec3ef15,0x3f6a09a7,0xbecf7bca,0x3f676bd8,0xbedae880,0x3f64aa59,0xbee63375,0x3f61c598,0xbef15aea,0x3f5ebe05,0xbefc5d27,0x3f5b941a,0xbf039c3d,0x3f584853,0xbf08f59b,
0x3f7ec46d,0xbdc8bd36,0x3f7e9bc9,0xbdd53db9,0x3f7e70b0,0xbde1bc2e,0x3f7e4323,0xbdee3876,0x3f7e1324,0xbdfab273,0x3f7de0b1,0xbe039502,0x3f7dabcc,0xbe09cf86,0x3f7d7474,0xbe1008b7,
0x3f61c598,0xbef15aea,0x3f5df6be,0xbeff17b2,0x3f59f26a,0xbf064b82,0x3f55b993,0xbf0cead0,0x3f514d3d,0xbf13682a,0x3f4cae79,0xbf19c200,0x3f47de65,0xbf1ff6cb,0x3f42de29,0xbf26050a,
0x3f7b14be,0xbe47c5c2,0x3f7a7302,0xbe541501,0x3f79c79d,0xbe605c13,0x3f791298,0xbe6c9a7f,0x3f7853f8,0xbe78cfcc,0x3f778bc5,0xbe827dc0,0x3f76ba07,0xbe888e93,0x3f75dec6,0xbe8e9a22,
0x3f54db31,0xbf0e39da,0x3f4f7a1f,0xbf15f6d9,0x3f49d112,0xbf1d7fd1,0x3f43e200,0xbf24d225,0x3f3daef9,0xbf2beb4a,0x3f373a23,0xbf32c8c9,0x3f3085bb,0xbf396842,0x3f299415,0xbf3fc767,
0x3f74fa0b,0xbe94a031,0x3f73913f,0xbe9d9e78,0x3f721352,0xbea68f12,0x3f708066,0xbeaf713a,0x3f6ed89e,0xbeb8442a,0x3f6d1c1d,0xbec1071e,0x3f6b4b0c,0xbec9b953,0x3f696591,0xbed25a09,
0x3f45e403,0xbf226799,0x3f3ebc1b,0xbf2ac082,0x3f373a23,0xbf32c8c9,0x3f2f61a5,0xbf3a7ca4,0x3f273656,0xbf41d870,0x3f1ebc12,0xbf48d8b3,0x3f15f6d9,0xbf4f7a1f,0x3f0cead0,0xbf55b993,
0x3f3504f3,0xbf3504f3,0x3f2beb4a,0xbf3daef9,0x3f226799,0xbf45e403,0x3f187fc0,0xbf4d9f02,0x3f0e39da,0xbf54db31,0x3f039c3d,0xbf5b941a,0x3ef15aea,0xbf61c598,0x3edae880,0xbf676bd8,
0x3ec3ef15,0xbf6c835e,0x3ea09ae5,0xbf731447,0x3e78cfcc,0xbf7853f8,0x3e2f10a2,0xbf7c3b28,0x3dc8bd36,0xbf7ec46d,0x3cc90ab0,0xbf7fec43,0xbd48fb30,0xbf7fb10f,0xbdfab273,0xbf7e1324,
0x3f226799,0xbf45e403,0x3f173c07,0xbf4e8d90,0x3f0b9a6b,0xbf5695e5,0x3eff17b2,0xbf5df6be,0x3ee63375,0xbf64aa59,0x3ecc9b8b,0xbf6aab7b,0x3eb263ef,0xbf6ff573,0x3e97a117,0xbf748422,
0x3e94a031,0xbf74fa0b,0x3e5a3997,0xbf7a1e84,0x3e09cf86,0xbf7dabcc,0x3d621469,0xbf7f9c18,0xbcc90ab0,0xbf7fec43,0xbdd53db9,0xbf7e9bc9,0xbe3b6ecf,0xbf7baccd,0xbe8586ce,0xbf772417,
0x3f0e39da,0xbf54db31,0x3f00e7e4,0xbf5d2d53,0x3ee63375,0xbf64aa59,0x3ec9b953,0xbf6b4b0c,0x3eac7cd4,0xbf710908,0x3e8e9a22,0xbf75dec6,0x3e605c13,0xbf79c79d,0x3e22abb6,0xbf7cbfc9,
0x3e47c5c2,0xbf7b14be,0x3de1bc2e,0xbf7e70b0,0x3cc90ab0,0xbf7fec43,0xbd7b2b74,0xbf7f84ab,0xbe164083,0xbf7d3aac,0xbe6c9a7f,0xbf791298,0xbea09ae5,0xbf731447,0xbec9b953,0xbf6b4b0c,
0x3ef15aea,0xbf61c598,0x3ed25a09,0xbf696591,0x3eb263ef,0xbf6ff573,0x3e919ddd,0xbf756d97,0x3e605c13,0xbf79c79d,0x3e1c76de,0xbf7cfe73,0x3dafb680,0xbf7f0e58,0x3c96c9b6,0xbf7ff4e6,
0x3dc8bd36,0xbf7ec46d,0x3bc90f88,0xbf7ffec4,0xbdafb680,0xbf7f0e58,0xbe354098,0xbf7bf531,0xbe888e93,0xbf76ba07,0xbeb554ec,0xbf6f6830,0xbee0924f,0xbf660f88,0xbf04f484,0xbf5ac450,
0x0,0xbf800000,0xbdc8bd36,0xbf7ec46d,0xbe47c5c2,0xbf7b14be,0xbe94a031,0xbf74fa0b,0xbec3ef15,0xbf6c835e,0xbef15aea,0xbf61c598,0xbf0e39da,0xbf54db31,0xbf226799,0xbf45e403,
0xbec3ef15,0xbf6c835e,0xbefc5d27,0xbf5ebe05,0xbf187fc0,0xbf4d9f02,0xbf3085bb,0xbf396842,0xbf45e403,0xbf226799,0xbf584853,0xbf08f59b,0xbf676bd8,0xbedae880,0xbf731447,0xbea09ae5,
0xbdc8bd36,0xbf7ec46d,0xbe4dee60,0xbf7ac516,0xbe9aa086,0xbf740bdd,0xbecc9b8b,0xbf6aab7b,0xbefc5d27,0xbf5ebe05,0xbf14b039,0xbf5064af,0xbf299415,0xbf3fc767,0xbf3ca003,0xbf2d1469,
0xbef15aea,0xbf61c598,0xbf14b039,0xbf5064af,0xbf2e3bde,0xbf3b8f3b,0xbf44e3f5,0xbf239da9,0xbf584853,0xbf08f59b,0xbf6816a8,0xbed8106b,0xbf740bdd,0xbe9aa086,0xbf7bf531,0xbe354098,
0xbe47c5c2,0xbf7b14be,0xbe9aa086,0xbf740bdd,0xbecf7bca,0xbf6a09a7,0xbf00e7e4,0xbf5d2d53,0xbf187fc0,0xbf4d9f02,0xbf2e3bde,0xbf3b8f3b,0xbf41d870,0xbf273656,0xbf531849,0xbf10d3cd,
0xbf0e39da,0xbf54db31,0xbf299415,0xbf3fc767,0xbf41d870,0xbf273656,0xbf5695e5,0xbf0b9a6b,0xbf676bd8,0xbedae880,0xbf740bdd,0xbe9aa086,0xbf7c3b28,0xbe2f10a2,0xbf7fd397,0xbd16c32c,
0xbe94a031,0xbf74fa0b,0xbecc9b8b,0xbf6aab7b,0xbf00e7e4,0xbf5d2d53,0xbf19c200,0xbf4cae79,0xbf3085bb,0xbf396842,0xbf44e3f5,0xbf239da9,0xbf5695e5,0xbf0b9a6b,0xbf655e0b,0xbee363fa,
0xbf226799,0xbf45e403,0xbf3ca003,0xbf2d1469,0xbf531849,0xbf10d3cd,0xbf655e0b,0xbee363fa,0xbf731447,0xbea09ae5,0xbf7bf531,0xbe354098,0xbf7fd397,0xbd16c32c,0xbf7e9bc9,0x3dd53db9,
0xbf3504f3,0xbf3504f3,0xbf4d9f02,0xbf187fc0,0xbf61c598,0xbef15aea,0xbf710908,0xbeac7cd4,0xbf7b14be,0xbe47c5c2,0xbf7fb10f,0xbd48fb30,0xbf7ec46d,0x3dc8bd36,0xbf7853f8,0x3e78cfcc,
0xbf6c835e,0xbec3ef15,0xbf79c79d,0xbe605c13,0xbf7fb10f,0xbd48fb30,0xbf7e1324,0x3dfab273,0xbf74fa0b,0x3e94a031,0xbf64aa59,0x3ee63375,0xbf4d9f02,0x3f187fc0,0xbf3085bb,0x3f396842,
0xbf45e403,0xbf226799,0xbf5c61c7,0xbf0242b1,0xbf6db293,0xbebe1d4a,0xbf796e4e,0xbe667c66,0xbf7f4e6d,0xbd96a905,0xbf7f2f9d,0x3da3308c,0xbf791298,0x3e6c9a7f,0xbf6d1c1d,0x3ec1071e,
0xbf74fa0b,0xbe94a031,0xbf7e4323,0xbdee3876,0xbf7f84ab,0x3d7b2b74,0xbf78b47b,0x3e72b651,0xbf6a09a7,0x3ecf7bca,0xbf53fac3,0x3f0f8784,0xbf373a23,0x3f32c8c9,0xbf14b039,0x3f5064af,
0xbf54db31,0xbf0e39da,0xbf68bf3c,0xbed53641,0xbf76ba07,0xbe888e93,0xbf7e70b0,0xbde1bc2e,0xbf7fb10f,0x3d48fb30,0xbf7a7302,0x3e541501,0xbf6ed89e,0x3eb8442a,0xbf5d2d53,0x3f00e7e4,
0xbf7b14be,0xbe47c5c2,0xbf7ffb11,0xbc490e90,0xbf7c3b28,0x3e2f10a2,0xbf6ff573,0x3eb263ef,0xbf5b941a,0x3f039c3d,0xbf3fc767,0x3f299415,0xbf1d7fd1,0x3f49d112,0xbeebcbbb,0x3f633c5a,
0xbf61c598,0xbef15aea,0xbf7294f8,0xbea395c5,0xbf7cbfc9,0xbe22abb6,0xbf7ffec4,0x3bc90f88,0xbf7c3b28,0x3e2f10a2,0xbf718f57,0x3ea986c4,0xbf604621,0x3ef6e0cb,0xbf48d8b3,0x3f1ebc12,
0xbf7ec46d,0xbdc8bd36,0xbf7eea9d,0x3dbc3ac3,0xbf75dec6,0x3e8e9a22,0xbf63f473,0x3ee900b7,0xbf49d112,0x3f1d7fd1,0xbf286605,0x3f40d0da,0xbf00e7e4,0x3f5d2d53,0xbea986c4,0x3f718f57,
0x3f800000,0x0,0x3f800000,0x0,0x3f800000,0x0,0x3f800000,0x0,0x3f800000,0x0,0x3f800000,0x0,0x3f800000,0x0,0x3f800000,0x0,
0x3f54db31,0xbf0e39da,0x3f514d3d,0xbf13682a,0x3f4d9f02,0xbf187fc0,0x3f49d112,0xbf1d7fd1,0x3f45e403,0xbf226799,0x3f41d870,0xbf273656,0x3f3daef9,0xbf2beb4a,0x3f396842,0xbf3085bb,
0x3f7d3aac,0xbe164083,0x3f7cfe73,0xbe1c76de,0x3f7cbfc9,0xbe22abb6,0x3f7c7eb0,0xbe28defc,0x3f7c3b28,0xbe2f10a2,0x3f7bf531,0xbe354098,0x3f7baccd,0xbe3b6ecf,0x3f7b61fc,0xbe419b37,
0x3f3daef9,0xbf2beb4a,0x3f385216,0xbf31a81d,0x3f32c8c9,0xbf373a23,0x3f2d1469,0xbf3ca003,0x3f273656,0xbf41d870,0x3f212ff9,0xbf46e22a,0x3f1b02c6,0xbf4bbbf8,0x3f14b039,0xbf5064af,
0x3f74fa0b,0xbe94a031,0x3f740bdd,0xbe9aa086,0x3f731447,0xbea09ae5,0x3f721352,0xbea68f12,0x3f710908,0xbeac7cd4,0x3f6ff573,0xbeb263ef,0x3f6ed89e,0xbeb8442a,0x3f6db293,0xbebe1d4a,
0x3f226799,0xbf45e403,0x3f1b02c6,0xbf4bbbf8,0x3f13682a,0xbf514d3d,0x3f0b9a6b,0xbf5695e5,0x3f039c3d,0xbf5b941a,0x3ef6e0cb,0xbf604621,0x3ee63375,0xbf64aa59,0x3ed53641,0xbf68bf3c,
0x3f676bd8,0xbedae880,0x3f655e0b,0xbee363fa,0x3f633c5a,0xbeebcbbb,0x3f6106f2,0xbef41f07,0x3f5ebe05,0xbefc5d27,0x3f5c61c7,0xbf0242b1,0x3f59f26a,0xbf064b82,0x3f577026,0xbf0a48ad,
0x3f039c3d,0xbf5b941a,0x3ef41f07,0xbf6106f2,0x3ee0924f,0xbf660f88,0x3ecc9b8b,0xbf6aab7b,0x3eb8442a,0xbf6ed89e,0x3ea395c5,0xbf7294f8,0x3e8e9a22,0xbf75dec6,0x3e72b651,0xbf78b47b,
0x3ec3ef15,0xbf6c835e,0x3eac7cd4,0xbf710908,0x3e94a031,0xbf74fa0b,0x3e78cfcc,0xbf7853f8,0x3e47c5c2,0xbf7b14be,0x3e164083,0xbf7d3aac,0x3dc8bd36,0xbf7ec46d,0x3d48fb30,0xbf7fb10f,
0xbe47c5c2,0xbf7b14be,0xbe888e93,0xbf76ba07,0xbeac7cd4,0xbf710908,0xbecf7bca,0xbf6a09a7,0xbef15aea,0xbf61c598,0xbf08f59b,0xbf584853,0xbf187fc0,0xbf4d9f02,0xbf273656,0xbf41d870,
0x3e78cfcc,0xbf7853f8,0x3e419b37,0xbf7b61fc,0x3e09cf86,0xbf7dabcc,0x3da3308c,0xbf7f2f9d,0x3cc90ab0,0xbf7fec43,0xbcfb49ba,0xbf7fe129,0xbdafb680,0xbf7f0e58,0xbe1008b7,0xbf7d7474,
0xbeac7cd4,0xbf710908,0xbed25a09,0xbf696591,0xbef6e0cb,0xbf604621,0xbf0cead0,0xbf55b993,0xbf1d7fd1,0xbf49d112,0xbf2d1469,0xbf3ca003,0xbf3b8f3b,0xbf2e3bde,0xbf48d8b3,0xbf1ebc12,
0x3dc8bd36,0xbf7ec46d,0x3d16c32c,0xbf7fd397,0xbcc90ab0,0xbf7fec43,0xbdafb680,0xbf7f0e58,0xbe164083,0xbf7d3aac,0xbe541501,0xbf7a7302,0xbe888e93,0xbf76ba07,0xbea68f12,0xbf721352,
0xbef15aea,0xbf61c598,0xbf0b9a6b,0xbf5695e5,0xbf1d7fd1,0xbf49d112,0xbf2e3bde,0xbf3b8f3b,0xbf3daef9,0xbf2beb4a,0xbf4bbbf8,0xbf1b02c6,0xbf584853,0xbf08f59b,0xbf633c5a,0xbeebcbbb,
0xbd48fb30,0xbf7fb10f,0xbdee3876,0xbf7e4323,0xbe3b6ecf,0xbf7baccd,0xbe7ee6e1,0xbf77f110,0xbea09ae5,0xbf731447,0xbec1071e,0xbf6d1c1d,0xbee0924f,0xbf660f88,0xbeff17b2,0xbf5df6be,
0xbf187fc0,0xbf4d9f02,0xbf2ac082,0xbf3ebc1b,0xbf3b8f3b,0xbf2e3bde,0xbf4ac77f,0xbf1c420c,0xbf584853,0xbf08f59b,0xbf63f473,0xbee900b7,0xbf6db293,0xbebe1d4a,0xbf756d97,0xbe919ddd,
0xbf3504f3,0xbf3504f3,0xbf45e403,0xbf226799,0xbf54db31,0xbf0e39da,0xbf61c598,0xbef15aea,0xbf6c835e,0xbec3ef15,0xbf74fa0b,0xbe94a031,0xbf7b14be,0xbe47c5c2,0xbf7ec46d,0xbdc8bd36,
0xbf7b14be,0xbe47c5c2,0xbf7f4e6d,0xbd96a905,0xbf7fb10f,0x3d48fb30,0xbf7c3b28,0x3e2f10a2,0xbf74fa0b,0x3e94a031,0xbf6a09a7,0x3ecf7bca,0xbf5b941a,0x3f039c3d,0xbf49d112,0x3f1d7fd1,
0xbf4d9f02,0xbf187fc0,0xbf5c61c7,0xbf0242b1,0xbf68bf3c,0xbed53641,0xbf7294f8,0xbea395c5,0xbf79c79d,0xbe605c13,0xbf7e4323,0xbdee3876,0xbf7ffb11,0xbc490e90,0xbf7eea9d,0x3dbc3ac3,
0xbf7fb10f,0xbd48fb30,0xbf7f2f9d,0x3da3308c,0xbf7a7302,0x3e541501,0xbf718f57,0x3ea986c4,0xbf64aa59,0x3ee63375,0xbf53fac3,0x3f0f8784,0xbf3fc767,0x3f299415,0xbf286605,0x3f40d0da,
0xbf61c598,0xbef15aea,0xbf6db293,0xbebe1d4a,0xbf76ba07,0xbe888e93,0xbf7cbfc9,0xbe22abb6,0xbf7fb10f,0xbd48fb30,0xbf7f84ab,0x3d7b2b74,0xbf7c3b28,0x3e2f10a2,0xbf75dec6,0x3e8e9a22,
0xbf7ec46d,0x3dc8bd36,0xbf791298,0x3e6c9a7f,0xbf6ed89e,0x3eb8442a,0xbf604621,0x3ef6e0cb,0xbf4d9f02,0x3f187fc0,0xbf373a23,0x3f32c8c9,0xbf1d7fd1,0x3f49d112,0xbf00e7e4,0x3f5d2d53,
0xbf710908,0xbeac7cd4,0xbf796e4e,0xbe667c66,0xbf7e70b0,0xbde1bc2e,0xbf7ffec4,0x3bc90f88,0xbf7e1324,0x3dfab273,0xbf78b47b,0x3e72b651,0xbf6ff573,0x3eb263ef,0xbf63f473,0x3ee900b7,
0xbf7853f8,0x3e78cfcc,0xbf6d1c1d,0x3ec1071e,0xbf5d2d53,0x3f00e7e4,0xbf48d8b3,0x3f1ebc12,0xbf3085bb,0x3f396842,0xbf14b039,0x3f5064af,0xbeebcbbb,0x3f633c5a,0xbea986c4,0x3f718f57,
0xbf6c835e,0x3ec3ef15,0xbf5b941a,0x3f039c3d,0xbf45e403,0x3f226799,0xbf2beb4a,0x3f3daef9,0xbf0e39da,0x3f54db31,0xbedae880,0x3f676bd8,0xbe94a031,0x3f74fa0b,0xbe164083,0x3f7d3aac,
0xbf0e39da,0x3f54db31,0xbecf7bca,0x3f6a09a7,0xbe78cfcc,0x3f7853f8,0xbd96a905,0x3f7f4e6d,0x3dc8bd36,0x3f7ec46d,0x3e888e93,0x3f76ba07,0x3edae880,0x3f676bd8,0x3f13682a,0x3f514d3d,
0xbf5b941a,0x3f039c3d,0xbf44e3f5,0x3f239da9,0xbf299415,0x3f3fc767,0xbf0a48ad,0x3f577026,0xbecf7bca,0x3f6a09a7,0xbe8586ce,0x3f772417,0xbde1bc2e,0x3f7e70b0,0x3d2fe007,0x3f7fc38f,
0xbedae880,0x3f676bd8,0xbe8586ce,0x3f772417,0xbdafb680,0x3f7f0e58,0x3dbc3ac3,0x3f7eea9d,0x3e888e93,0x3f76ba07,0x3eddbe79,0x3f66becc,0x3f15f6d9,0x3f4f7a1f,0x3f385216,0x3f31a81d,
0xbf45e403,0x3f226799,0xbf299415,0x3f3fc767,0xbf08f59b,0x3f584853,0xbec9b953,0x3f6b4b0c,0xbe78cfcc,0x3f7853f8,0xbdafb680,0x3f7f0e58,0x3d96a905,0x3f7f4e6d,0x3e6c9a7f,0x3f791298,
0xbe94a031,0x3f74fa0b,0xbde1bc2e,0x3f7e70b0,0x3d96a905,0x3f7f4e6d,0x3e827dc0,0x3f778bc5,0x3edae880,0x3f676bd8,0x3f15f6d9,0x3f4f7a1f,0x3f396842,0x3f3085bb,0x3f5695e5,0x3f0b9a6b,
0xbf2beb4a,0x3f3daef9,0xbf0a48ad,0x3f577026,0xbec9b953,0x3f6b4b0c,0xbe72b651,0x3f78b47b,0xbd96a905,0x3f7f4e6d,0x3dbc3ac3,0x3f7eea9d,0x3e827dc0,0x3f778bc5,0x3ed25a09,0x3f696591,
0xbe164083,0x3f7d3aac,0x3d2fe007,0x3f7fc38f,0x3e6c9a7f,0x3f791298,0x3ed25a09,0x3f696591,0x3f13682a,0x3f514d3d,0x3f385216,0x3f31a81d,0x3f5695e5,0x3f0b9a6b,0x3f6d1c1d,0x3ec1071e,
0x3d803d80,0x3e00,0x3e00,0x3e00,0x3e00,0x3e00,0x3e00,0x3e00,0x3e00,0x3e00,0x3e00,0x3e00,0x3e00,0x3e00,0x3e00,0x3e00,
0xbd803d80,0xbe000000,0xbcc83dfb,0x3cc8bdfb,0xbd443ded,0xbdedbd44,0xbdd53d8e,0x3dd5bd8e,0xbdb53db5,0xbdb5bdb5,0xbdfbbcc8,0x3dfb3cc8,0xbded3d44,0xbd44bded,0xbd8ebdd5,0x3d8e3dd5,
0x3d803d80,0xbe00,0xbd443ded,0xbd443ded,0xbdb53db5,0x3db5bdb5,0xbdedbd44,0xbdedbd44,0xbe000000,0x3e000000,0x3d44bded,0x3d44bded,0xbdb5bdb5,0x3db53db5,0x3ded3d44,0x3ded3d44,
0xbd803d80,0x3e000000,0xbd8e3dd5,0x3d8ebdd5,0xbded3d44,0x3d443ded,0xbcc8bdfb,0x3cc83dfb,0xbdb5bdb5,0xbdb53db5,0x3dd53d8e,0xbdd5bd8e,0x3d44bded,0xbdedbd44,0xbdfb3cc8,0x3dfbbcc8,
0x3d803d80,0x3e00,0xbdb53db5,0xbdb53db5,0xbe000000,0xbe000000,0x3db5bdb5,0x3db5bdb5,0xbe00,0xbe00,0xbdb53db5,0xbdb53db5,0x3e000000,0x3e000000,0x3db5bdb5,0x3db5bdb5,
0xbd803d80,0xbe000000,0xbdd53d8e,0x3dd5bd8e,0xbdedbd44,0x3d44bded,0x3dfb3cc8,0xbdfbbcc8,0x3db5bdb5,0x3db53db5,0xbd8ebdd5,0x3d8e3dd5,0x3d443ded,0xbded3d44,0xbcc83dfb,0x3cc8bdfb,
0x3d803d80,0xbe00,0xbded3d44,0xbded3d44,0xbdb5bdb5,0x3db53db5,0x3d443ded,0x3d443ded,0x3e000000,0xbe000000,0x3dedbd44,0x3dedbd44,0xbdb53db5,0x3db5bdb5,0xbd44bded,0xbd44bded,
0xbd803d80,0x3e000000,0xbdfb3cc8,0x3dfbbcc8,0xbd44bded,0xbded3d44,0xbd8e3dd5,0x3d8ebdd5,0x3db53db5,0x3db5bdb5,0x3cc83dfb,0xbcc8bdfb,0xbdedbd44,0xbd443ded,0x3dd53d8e,0xbdd5bd8e,
0x3d803d80,0x3e00,0xbe000000,0xbe000000,0xbe00,0xbe00,0xbe000000,0xbe000000,0x3e00,0x3e00,0xbe000000,0xbe000000,0xbe00,0xbe00,0xbe000000,0xbe000000,
0xbd803d80,0xbe000000,0xbdfbbcc8,0x3dfb3cc8,0x3d44bded,0x3ded3d44,0xbd8ebdd5,0x3d8e3dd5,0xbdb53db5,0xbdb5bdb5,0x3cc8bdfb,0xbcc83dfb,0x3dedbd44,0x3d443ded,0x3dd5bd8e,0xbdd53d8e,
0x3d803d80,0xbe00,0xbdedbd44,0xbdedbd44,0x3db5bdb5,0xbdb53db5,0x3d44bded,0x3d44bded,0xbe000000,0x3e000000,0x3ded3d44,0x3ded3d44,0x3db53db5,0xbdb5bdb5,0xbd443ded,0xbd443ded,
0xbd803d80,0x3e000000,0xbdd5bd8e,0x3dd53d8e,0x3dedbd44,0xbd44bded,0x3dfbbcc8,0xbdfb3cc8,0xbdb5bdb5,0xbdb53db5,0xbd8e3dd5,0x3d8ebdd5,0xbd443ded,0x3ded3d44,0xbcc8bdfb,0x3cc83dfb,
0x3d803d80,0x3e00,0xbdb5bdb5,0xbdb5bdb5,0x3e000000,0x3e000000,0x3db53db5,0x3db53db5,0xbe00,0xbe00,0xbdb5bdb5,0xbdb5bdb5,0xbe000000,0xbe000000,0x3db53db5,0x3db53db5,
0xbd803d80,0xbe000000,0xbd8ebdd5,0x3d8e3dd5,0x3ded3d44,0xbd443ded,0xbcc83dfb,0x3cc8bdfb,0x3db5bdb5,0x3db53db5,0x3dd5bd8e,0xbdd53d8e,0xbd44bded,0x3dedbd44,0xbdfbbcc8,0x3dfb3cc8,
0x3d803d80,0xbe00,0xbd44bded,0xbd44bded,0x3db53db5,0xbdb5bdb5,0xbded3d44,0xbded3d44,0x3e000000,0xbe000000,0x3d443ded,0x3d443ded,0x3db5bdb5,0xbdb53db5,0x3dedbd44,0x3dedbd44,
0xbd803d80,0x3e000000,0xbcc8bdfb,0x3cc83dfb,0x3d443ded,0x3dedbd44,0xbdd5bd8e,0x3dd53d8e,0x3db53db5,0x3db5bdb5,0xbdfb3cc8,0x3dfbbcc8,0x3ded3d44,0x3d44bded,0xbd8e3dd5,0x3d8ebdd5,
0x3d803d80,0x3e00,0xbe00,0xbe00,0x3e00,0x3e00,0xbe00,0xbe00,0x3e00,0x3e00,0xbe00,0xbe00,0x3e00,0x3e00,0xbe00,0xbe00,
0xbd803d80,0xbe000000,0x3cc8bdfb,0xbcc83dfb,0xbd443ded,0xbdedbd44,0x3dd5bd8e,0xbdd53d8e,0xbdb53db5,0xbdb5bdb5,0x3dfb3cc8,0xbdfbbcc8,0xbded3d44,0xbd44bded,0x3d8e3dd5,0xbd8ebdd5,
0x3d803d80,0xbe00,0x3d44bded,0x3d44bded,0xbdb53db5,0x3db5bdb5,0x3ded3d44,0x3ded3d44,0xbe000000,0x3e000000,0xbd443ded,0xbd443ded,0xbdb5bdb5,0x3db53db5,0xbdedbd44,0xbdedbd44,
0xbd803d80,0x3e000000,0x3d8ebdd5,0xbd8e3dd5,0xbded3d44,0x3d443ded,0x3cc83dfb,0xbcc8bdfb,0xbdb5bdb5,0xbdb53db5,0xbdd5bd8e,0x3dd53d8e,0x3d44bded,0xbdedbd44,0x3dfbbcc8,0xbdfb3cc8,
0x3d803d80,0x3e00,0x3db5bdb5,0x3db5bdb5,0xbe000000,0xbe000000,0xbdb53db5,0xbdb53db5,0xbe00,0xbe00,0x3db5bdb5,0x3db5bdb5,0x3e000000,0x3e000000,0xbdb53db5,0xbdb53db5,
0xbd803d80,0xbe000000,0x3dd5bd8e,0xbdd53d8e,0xbdedbd44,0x3d44bded,0xbdfbbcc8,0x3dfb3cc8,0x3db5bdb5,0x3db53db5,0x3d8e3dd5,0xbd8ebdd5,0x3d443ded,0xbded3d44,0x3cc8bdfb,0xbcc83dfb,
0x3d803d80,0xbe00,0x3dedbd44,0x3dedbd44,0xbdb5bdb5,0x3db53db5,0xbd44bded,0xbd44bded,0x3e000000,0xbe000000,0xbded3d44,0xbded3d44,0xbdb53db5,0x3db5bdb5,0x3d443ded,0x3d443ded,
0xbd803d80,0x3e000000,0x3dfbbcc8,0xbdfb3cc8,0xbd44bded,0xbded3d44,0x3d8ebdd5,0xbd8e3dd5,0x3db53db5,0x3db5bdb5,0xbcc8bdfb,0x3cc83dfb,0xbdedbd44,0xbd443ded,0xbdd5bd8e,0x3dd53d8e,
0x3d803d80,0x3e00,0x3e000000,0x3e000000,0xbe00,0xbe00,0x3e000000,0x3e000000,0x3e00,0x3e00,0x3e000000,0x3e000000,0xbe00,0xbe00,0x3e000000,0x3e000000,
0xbd803d80,0xbe000000,0x3dfb3cc8,0xbdfbbcc8,0x3d44bded,0x3ded3d44,0x3d8e3dd5,0xbd8ebdd5,0xbdb53db5,0xbdb5bdb5,0xbcc83dfb,0x3cc8bdfb,0x3dedbd44,0x3d443ded,0xbdd53d8e,0x3dd5bd8e,
0x3d803d80,0xbe00,0x3ded3d44,0x3ded3d44,0x3db5bdb5,0xbdb53db5,0xbd443ded,0xbd443ded,0xbe000000,0x3e000000,0xbdedbd44,0xbdedbd44,0x3db53db5,0xbdb5bdb5,0x3d44bded,0x3d44bded,
0xbd803d80,0x3e000000,0x3dd53d8e,0xbdd5bd8e,0x3dedbd44,0xbd44bded,0xbdfb3cc8,0x3dfbbcc8,0xbdb5bdb5,0xbdb53db5,0x3d8ebdd5,0xbd8e3dd5,0xbd443ded,0x3ded3d44,0x3cc83dfb,0xbcc8bdfb,
0x3d803d80,0x3e00,0x3db53db5,0x3db53db5,0x3e000000,0x3e000000,0xbdb5bdb5,0xbdb5bdb5,0xbe00,0xbe00,0x3db53db5,0x3db53db5,0xbe000000,0xbe000000,0xbdb5bdb5,0xbdb5bdb5,
0xbd803d80,0xbe000000,0x3d8e3dd5,0xbd8ebdd5,0x3ded3d44,0xbd443ded,0x3cc8bdfb,0xbcc83dfb,0x3db5bdb5,0x3db53db5,0xbdd53d8e,0x3dd5bd8e,0xbd44bded,0x3dedbd44,0x3dfb3cc8,0xbdfbbcc8,
0x3d803d80,0xbe00,0x3d443ded,0x3d443ded,0x3db53db5,0xbdb5bdb5,0x3dedbd44,0x3dedbd44,0x3e000000,0xbe000000,0xbd44bded,0xbd44bded,0x3db5bdb5,0xbdb53db5,0xbded3d44,0xbded3d44,
0xbd803d80,0x3e000000,0x3cc83dfb,0xbcc8bdfb,0x3d443ded,0x3dedbd44,0x3dd53d8e,0xbdd5bd8e,0x3db53db5,0x3db5bdb5,0x3dfbbcc8,0xbdfb3cc8,0x3ded3d44,0x3d44bded,0x3d8ebdd5,0xbd8e3dd5,
0x3e00,0x3e00,0x3e00,0x3e00,0x3e00,0x3e00,0x3e00,0x3e00,0x3e00,0x3e00,0x3e00,0x3e00,0x3e00,0x3e00,0x3e00,0x3e00,
0xbc493dff,0x3c49bdff,0xbd153df5,0x3d15bdf5,0xbdc63da2,0x3dc6bda2,0xbde23d71,0x3de2bd71,0xbdffbc49,0x3dff3c49,0xbdf5bd15,0x3df53d15,0xbda2bdc6,0x3da23dc6,0xbd71bde2,0x3d713de2,
0xbcc83dfb,0xbcc83dfb,0xbd8e3dd5,0xbd8e3dd5,0xbdfbbcc8,0xbdfbbcc8,0xbdd5bd8e,0xbdd5bd8e,0x3cc8bdfb,0x3cc8bdfb,0x3d8ebdd5,0x3d8ebdd5,0x3dfb3cc8,0x3dfb3cc8,0x3dd53d8e,0x3dd53d8e,
0xbd153df5,0x3d15bdf5,0xbdc63da2,0x3dc6bda2,0xbd71bde2,0x3d713de2,0x3c49bdff,0xbc493dff,0x3df53d15,0xbdf5bd15,0x3da23dc6,0xbda2bdc6,0xbde23d71,0x3de2bd71,0xbdffbc49,0x3dff3c49,
0xbd443ded,0xbd443ded,0xbded3d44,0xbded3d44,0x3d44bded,0x3d44bded,0x3dedbd44,0x3dedbd44,0xbd443ded,0xbd443ded,0xbded3d44,0xbded3d44,0x3d44bded,0x3d44bded,0x3dedbd44,0x3dedbd44,
0xbd713de2,0x3d71bde2,0xbdff3c49,0x3dffbc49,0x3df5bd15,0xbdf53d15,0x3dc63da2,0xbdc6bda2,0xbde2bd71,0x3de23d71,0xbc49bdff,0x3c493dff,0x3d153df5,0xbd15bdf5,0xbda23dc6,0x3da2bdc6,
0xbd8e3dd5,0xbd8e3dd5,0xbdfbbcc8,0xbdfbbcc8,0x3dd53d8e,0x3dd53d8e,0xbcc83dfb,0xbcc83dfb,0x3d8ebdd5,0x3d8ebdd5,0x3dfb3cc8,0x3dfb3cc8,0xbdd5bd8e,0xbdd5bd8e,0x3cc8bdfb,0x3cc8bdfb,
0xbda23dc6,0x3da2bdc6,0xbde2bd71,0x3de23d71,0x3c493dff,0xbc49bdff,0xbdf53d15,0x3df5bd15,0x3dc63da2,0xbdc6bda2,0xbd713de2,0x3d71bde2,0x3dffbc49,0xbdff3c49,0x3d153df5,0xbd15bdf5,
0xbdb53db5,0xbdb53db5,0xbdb5bdb5,0xbdb5bdb5,0xbdb53db5,0xbdb53db5,0xbdb5bdb5,0xbdb5bdb5,0xbdb53db5,0xbdb53db5,0xbdb5bdb5,0xbdb5bdb5,0xbdb53db5,0xbdb53db5,0xbdb5bdb5,0xbdb5bdb5,
0xbdc63da2,0x3dc6bda2,0xbd71bde2,0x3d713de2,0xbdffbc49,0x3dff3c49,0x3d15bdf5,0xbd153df5,0xbda2bdc6,0x3da23dc6,0x3de2bd71,0xbde23d71,0x3c49bdff,0xbc493dff,0x3df53d15,0xbdf5bd15,
0xbdd53d8e,0xbdd53d8e,0xbcc8bdfb,0xbcc8bdfb,0xbd8ebdd5,0xbd8ebdd5,0x3dfbbcc8,0x3dfbbcc8,0x3dd5bd8e,0x3dd5bd8e,0x3cc83dfb,0x3cc83dfb,0x3d8e3dd5,0x3d8e3dd5,0xbdfb3cc8,0xbdfb3cc8,
0xbde23d71,0x3de2bd71,0x3c49bdff,0xbc493dff,0x3d15bdf5,0xbd153df5,0x3da23dc6,0xbda2bdc6,0x3d713de2,0xbd71bde2,0xbdffbc49,0x3dff3c49,0xbdf5bd15,0x3df53d15,0x3dc6bda2,0xbdc63da2,
0xbded3d44,0xbded3d44,0x3d44bded,0x3d44bded,0x3dedbd44,0x3dedbd44,0xbd443ded,0xbd443ded,0xbded3d44,0xbded3d44,0x3d44bded,0x3d44bded,0x3dedbd44,0x3dedbd44,0xbd443ded,0xbd443ded,
0xbdf53d15,0x3df5bd15,0x3da2bdc6,0xbda23dc6,0x3de23d71,0xbde2bd71,0xbdff3c49,0x3dffbc49,0xbd15bdf5,0x3d153df5,0x3dc63da2,0xbdc6bda2,0xbd713de2,0x3d71bde2,0xbc49bdff,0x3c493dff,
0xbdfb3cc8,0xbdfb3cc8,0x3dd5bd8e,0x3dd5bd8e,0x3cc83dfb,0x3cc83dfb,0xbd8ebdd5,0xbd8ebdd5,0x3dfbbcc8,0x3dfbbcc8,0xbdd53d8e,0xbdd53d8e,0xbcc8bdfb,0xbcc8bdfb,0x3d8e3dd5,0x3d8e3dd5,
0xbdff3c49,0x3dffbc49,0x3df5bd15,0xbdf53d15,0xbda23dc6,0x3da2bdc6,0x3d71bde2,0xbd713de2,0x3c493dff,0xbc49bdff,0xbd15bdf5,0x3d153df5,0x3dc63da2,0xbdc6bda2,0xbde2bd71,0x3de23d71,
0xbe000000,0xbe000000,0x3e000000,0x3e000000,0xbe000000,0xbe000000,0x3e000000,0x3e000000,0xbe000000,0xbe000000,0x3e000000,0x3e000000,0xbe000000,0xbe000000,0x3e000000,0x3e000000,
0xbdffbc49,0x3dff3c49,0x3df53d15,0xbdf5bd15,0xbda2bdc6,0x3da23dc6,0x3d713de2,0xbd71bde2,0x3c49bdff,0xbc493dff,0xbd153df5,0x3d15bdf5,0x3dc6bda2,0xbdc63da2,0xbde23d71,0x3de2bd71,
0xbdfbbcc8,0xbdfbbcc8,0x3dd53d8e,0x3dd53d8e,0x3cc8bdfb,0x3cc8bdfb,0xbd8e3dd5,0xbd8e3dd5,0x3dfb3cc8,0x3dfb3cc8,0xbdd5bd8e,0xbdd5bd8e,0xbcc83dfb,0xbcc83dfb,0x3d8ebdd5,0x3d8ebdd5,
0xbdf5bd15,0x3df53d15,0x3da23dc6,0xbda2bdc6,0x3de2bd71,0xbde23d71,0xbdffbc49,0x3dff3c49,0xbd153df5,0x3d15bdf5,0x3dc6bda2,0xbdc63da2,0xbd71bde2,0x3d713de2,0xbc493dff,0x3c49bdff,
0xbdedbd44,0xbdedbd44,0x3d443ded,0x3d443ded,0x3ded3d44,0x3ded3d44,0xbd44bded,0xbd44bded,0xbdedbd44,0xbdedbd44,0x3d443ded,0x3d443ded,0x3ded3d44,0x3ded3d44,0xbd44bded,0xbd44bded,
0xbde2bd71,0x3de23d71,0x3c493dff,0xbc49bdff,0x3d153df5,0xbd15bdf5,0x3da2bdc6,0xbda23dc6,0x3d71bde2,0xbd713de2,0xbdff3c49,0x3dffbc49,0xbdf53d15,0x3df5bd15,0x3dc63da2,0xbdc6bda2,
0xbdd5bd8e,0xbdd5bd8e,0xbcc83dfb,0xbcc83dfb,0xbd8e3dd5,0xbd8e3dd5,0x3dfb3cc8,0x3dfb3cc8,0x3dd53d8e,0x3dd53d8e,0x3cc8bdfb,0x3cc8bdfb,0x3d8ebdd5,0x3d8ebdd5,0xbdfbbcc8,0xbdfbbcc8,
0xbdc6bda2,0x3dc63da2,0xbd713de2,0x3d71bde2,0xbdff3c49,0x3dffbc49,0x3d153df5,0xbd15bdf5,0xbda23dc6,0x3da2bdc6,0x3de23d71,0xbde2bd71,0x3c493dff,0xbc49bdff,0x3df5bd15,0xbdf53d15,
0xbdb5bdb5,0xbdb5bdb5,0xbdb53db5,0xbdb53db5,0xbdb5bdb5,0xbdb5bdb5,0xbdb53db5,0xbdb53db5,0xbdb5bdb5,0xbdb5bdb5,0xbdb53db5,0xbdb53db5,0xbdb5bdb5,0xbdb5bdb5,0xbdb53db5,0xbdb53db5,
0xbda2bdc6,0x3da23dc6,0xbde23d71,0x3de2bd71,0x3c49bdff,0xbc493dff,0xbdf5bd15,0x3df53d15,0x3dc6bda2,0xbdc63da2,0xbd71bde2,0x3d713de2,0x3dff3c49,0xbdffbc49,0x3d15bdf5,0xbd153df5,
0xbd8ebdd5,0xbd8ebdd5,0xbdfb3cc8,0xbdfb3cc8,0x3dd5bd8e,0x3dd5bd8e,0xbcc8bdfb,0xbcc8bdfb,0x3d8e3dd5,0x3d8e3dd5,0x3dfbbcc8,0x3dfbbcc8,0xbdd53d8e,0xbdd53d8e,0x3cc83dfb,0x3cc83dfb,
0xbd71bde2,0x3d713de2,0xbdffbc49,0x3dff3c49,0x3df53d15,0xbdf5bd15,0x3dc6bda2,0xbdc63da2,0xbde23d71,0x3de2bd71,0xbc493dff,0x3c49bdff,0x3d15bdf5,0xbd153df5,0xbda2bdc6,0x3da23dc6,
0xbd44bded,0xbd44bded,0xbdedbd44,0xbdedbd44,0x3d443ded,0x3d443ded,0x3ded3d44,0x3ded3d44,0xbd44bded,0xbd44bded,0xbdedbd44,0xbdedbd44,0x3d443ded,0x3d443ded,0x3ded3d44,0x3ded3d44,
0xbd15bdf5,0x3d153df5,0xbdc6bda2,0x3dc63da2,0xbd713de2,0x3d71bde2,0x3c493dff,0xbc49bdff,0x3df5bd15,0xbdf53d15,0x3da2bdc6,0xbda23dc6,0xbde2bd71,0x3de23d71,0xbdff3c49,0x3dffbc49,
0xbcc8bdfb,0xbcc8bdfb,0xbd8ebdd5,0xbd8ebdd5,0xbdfb3cc8,0xbdfb3cc8,0xbdd53d8e,0xbdd53d8e,0x3cc83dfb,0x3cc83dfb,0x3d8e3dd5,0x3d8e3dd5,0x3dfbbcc8,0x3dfbbcc8,0x3dd5bd8e,0x3dd5bd8e,
0xbc49bdff,0x3c493dff,0xbd15bdf5,0x3d153df5,0xbdc6bda2,0x3dc63da2,0xbde2bd71,0x3de23d71,0xbdff3c49,0x3dffbc49,0xbdf53d15,0x3df5bd15,0xbda23dc6,0x3da2bdc6,0xbd713de2,0x3d71bde2,
0xbdb53d80,0xbd443ded,0xbbc93e00,0xbdbe3dac,0xbc493dff,0xbd713de2,0xbcf93df8,0xbddc3d84,0xbcc83dfb,0xbd8e3dd5,0xbd5b3de7,0xbdf13d2c,0xbd153df5,0xbda23dc6,0xbd983dce,0xbdfd3c96,
0x3db53d80,0xbdedbd44,0xbcf93df8,0x3ddcbd84,0xbd713de2,0xbda2bdc6,0xbdf13d2c,0x3de73d5b,0xbdd53d8e,0xbcc8bdfb,0xbdcebd98,0x3c963dfd,0xbdff3c49,0x3d15bdf5,0x3bc9be00,0xbdbe3dac,
0xbdb53d80,0x3d44bded,0xbd5b3de7,0xbdf13d2c,0xbdc63da2,0x3df5bd15,0xbdcebd98,0xbc96bdfd,0xbdfbbcc8,0x3dd53d8e,0x3dbebdac,0x3e003bc9,0xbd71bde2,0x3c493dff,0x3d843ddc,0xbcf93df8,
0x3db53d80,0x3ded3d44,0xbd983dce,0x3dfdbc96,0xbdf53d15,0xbc493dff,0x3bc9be00,0xbdbe3dac,0xbd8ebdd5,0xbdfb3cc8,0x3d843ddc,0x3cf9bdf8,0x3da2bdc6,0xbd71bde2,0xbde7bd5b,0x3d2c3df1,
0xbdb53d80,0xbd443ded,0xbdbe3dac,0xbe00bbc9,0xbdffbc49,0xbde2bd71,0x3ddcbd84,0x3df83cf9,0x3cc8bdfb,0x3d8ebdd5,0xbdf13d2c,0xbde7bd5b,0x3df53d15,0x3dc63da2,0x3dfdbc96,0x3dce3d98,
0x3db53d80,0xbdedbd44,0xbddc3d84,0x3df83cf9,0xbde2bd71,0x3dc6bda2,0x3de73d5b,0xbd2cbdf1,0x3dd5bd8e,0x3cc83dfb,0xbc96bdfd,0xbd983dce,0x3c493dff,0xbdf5bd15,0xbdbe3dac,0x3e003bc9,
0xbdb53d80,0x3d44bded,0xbdf13d2c,0xbde7bd5b,0xbda2bdc6,0x3d153df5,0x3c963dfd,0xbd983dce,0x3dfb3cc8,0xbdd5bd8e,0x3e003bc9,0x3dac3dbe,0xbde23d71,0x3dffbc49,0x3cf9bdf8,0x3ddcbd84,
0x3db53d80,0x3ded3d44,0xbdfd3c96,0x3dce3d98,0xbd15bdf5,0xbdffbc49,0xbdbe3dac,0x3e003bc9,0x3d8e3dd5,0x3dfbbcc8,0xbcf93df8,0x3ddcbd84,0xbdc6bda2,0xbde23d71,0x3d2c3df1,0x3d5bbde7,
0xbdb53d80,0xbd443ded,0xbe00bbc9,0xbdacbdbe,0x3c49bdff,0x3d71bde2,0xbdf8bcf9,0xbd84bddc,0xbcc83dfb,0xbd8e3dd5,0xbde7bd5b,0xbd2cbdf1,0x3d15bdf5,0x3da2bdc6,0xbdcebd98,0xbc96bdfd,
0x3db53d80,0xbdedbd44,0xbdf8bcf9,0x3d843ddc,0x3d71bde2,0x3da23dc6,0xbd2cbdf1,0xbd5b3de7,0xbdd53d8e,0xbcc8bdfb,0x3d98bdce,0xbdfd3c96,0x3dffbc49,0xbd153df5,0x3e003bc9,0xbdacbdbe,
0xbdb53d80,0x3d44bded,0xbde7bd5b,0xbd2cbdf1,0x3dc6bda2,0xbdf53d15,0x3d98bdce,0x3dfdbc96,0xbdfbbcc8,0x3dd53d8e,0x3dac3dbe,0xbbc93e00,0x3d713de2,0xbc49bdff,0xbddc3d84,0xbdf8bcf9,
0x3db53d80,0x3ded3d44,0xbdcebd98,0x3c963dfd,0x3df5bd15,0x3c49bdff,0x3e003bc9,0xbdacbdbe,0xbd8ebdd5,0xbdfb3cc8,0xbddc3d84,0x3df83cf9,0xbda23dc6,0x3d713de2,0x3d5bbde7,0xbdf13d2c,
0xbdb53d80,0xbd443ded,0xbdacbdbe,0x3bc9be00,0x3dff3c49,0x3de23d71,0x3d843ddc,0xbcf93df8,0x3cc8bdfb,0x3d8ebdd5,0xbd2cbdf1,0x3d5bbde7,0xbdf5bd15,0xbdc6bda2,0x3c963dfd,0xbd983dce,
0x3db53d80,0xbdedbd44,0xbd84bddc,0xbcf93df8,0x3de23d71,0xbdc63da2,0xbd5b3de7,0x3df1bd2c,0x3dd5bd8e,0x3cc83dfb,0x3dfdbc96,0xbdcebd98,0xbc49bdff,0x3df53d15,0xbdacbdbe,0xbbc93e00,
0xbdb53d80,0x3d44bded,0xbd2cbdf1,0x3d5bbde7,0x3da23dc6,0xbd15bdf5,0xbdfd3c96,0xbdcebd98,0x3dfb3cc8,0xbdd5bd8e,0xbbc93e00,0xbdbe3dac,0x3de2bd71,0xbdff3c49,0x3df83cf9,0x3d843ddc,
0x3db53d80,0x3ded3d44,0xbc96bdfd,0xbd983dce,0x3d153df5,0x3dff3c49,0xbdacbdbe,0xbbc93e00,0x3d8e3dd5,0x3dfbbcc8,0xbdf8bcf9,0x3d843ddc,0x3dc63da2,0x3de2bd71,0xbdf13d2c,0x3de73d5b,
0xbdb53d80,0xbd443ded,0x3bc9be00,0x3dbebdac,0xbc493dff,0xbd713de2,0x3cf9bdf8,0x3ddcbd84,0xbcc83dfb,0xbd8e3dd5,0x3d5bbde7,0x3df1bd2c,0xbd153df5,0xbda23dc6,0x3d98bdce,0x3dfdbc96,
0x3db53d80,0xbdedbd44,0x3cf9bdf8,0xbddc3d84,0xbd713de2,0xbda2bdc6,0x3df1bd2c,0xbde7bd5b,0xbdd53d8e,0xbcc8bdfb,0x3dce3d98,0xbc96bdfd,0xbdff3c49,0x3d15bdf5,0xbbc93e00,0x3dbebdac,
0xbdb53d80,0x3d44bded,0x3d5bbde7,0x3df1bd2c,0xbdc63da2,0x3df5bd15,0x3dce3d98,0x3c963dfd,0xbdfbbcc8,0x3dd53d8e,0xbdbe3dac,0xbe00bbc9,0xbd71bde2,0x3c493dff,0xbd84bddc,0x3cf9bdf8,
0x3db53d80,0x3ded3d44,0x3d98bdce,0xbdfd3c96,0xbdf53d15,0xbc493dff,0xbbc93e00,0x3dbebdac,0xbd8ebdd5,0xbdfb3cc8,0xbd84bddc,0xbcf93df8,0x3da2bdc6,0xbd71bde2,0x3de73d5b,0xbd2cbdf1,
0xbdb53d80,0xbd443ded,0x3dbebdac,0x3e003bc9,0xbdffbc49,0xbde2bd71,0xbddc3d84,0xbdf8bcf9,0x3cc8bdfb,0x3d8ebdd5,0x3df1bd2c,0x3de73d5b,0x3df53d15,0x3dc63da2,0xbdfd3c96,0xbdcebd98,
0x3db53d80,0xbdedbd44,0x3ddcbd84,0xbdf8bcf9,0xbde2bd71,0x3dc6bda2,0xbde7bd5b,0x3d2c3df1,0x3dd5bd8e,0x3cc83dfb,0x3c963dfd,0x3d98bdce,0x3c493dff,0xbdf5bd15,0x3dbebdac,0xbe00bbc9,
0xbdb53d80,0x3d44bded,0x3df1bd2c,0x3de73d5b,0xbda2bdc6,0x3d153df5,0xbc96bdfd,0x3d98bdce,0x3dfb3cc8,0xbdd5bd8e,0xbe00bbc9,0xbdacbdbe,0xbde23d71,0x3dffbc49,0xbcf93df8,0xbddc3d84,
0x3db53d80,0x3ded3d44,0x3dfdbc96,0xbdcebd98,0xbd15bdf5,0xbdffbc49,0x3dbebdac,0xbe00bbc9,0x3d8e3dd5,0x3dfbbcc8,0x3cf9bdf8,0xbddc3d84,0xbdc6bda2,0xbde23d71,0xbd2cbdf1,0xbd5b3de7,
0xbdb53d80,0xbd443ded,0x3e003bc9,0x3dac3dbe,0x3c49bdff,0x3d71bde2,0x3df83cf9,0x3d843ddc,0xbcc83dfb,0xbd8e3dd5,0x3de73d5b,0x3d2c3df1,0x3d15bdf5,0x3da2bdc6,0x3dce3d98,0x3c963dfd,
0x3db53d80,0xbdedbd44,0x3df83cf9,0xbd84bddc,0x3d71bde2,0x3da23dc6,0x3d2c3df1,0x3d5bbde7,0xbdd53d8e,0xbcc8bdfb,0xbd983dce,0x3dfdbc96,0x3dffbc49,0xbd153df5,0xbe00bbc9,0x3dac3dbe,
0xbdb53d80,0x3d44bded,0x3de73d5b,0x3d2c3df1,0x3dc6bda2,0xbdf53d15,0xbd983dce,0xbdfd3c96,0xbdfbbcc8,0x3dd53d8e,0xbdacbdbe,0x3bc9be00,0x3d713de2,0xbc49bdff,0x3ddcbd84,0x3df83cf9,
0x3db53d80,0x3ded3d44,0x3dce3d98,0xbc96bdfd,0x3df5bd15,0x3c49bdff,0xbe00bbc9,0x3dac3dbe,0xbd8ebdd5,0xbdfb3cc8,0x3ddcbd84,0xbdf8bcf9,0xbda23dc6,0x3d713de2,0xbd5b3de7,0x3df1bd2c,
0xbdb53d80,0xbd443ded,0x3dac3dbe,0xbbc93e00,0x3dff3c49,0x3de23d71,0xbd84bddc,0x3cf9bdf8,0x3cc8bdfb,0x3d8ebdd5,0x3d2c3df1,0xbd5b3de7,0xbdf5bd15,0xbdc6bda2,0xbc96bdfd,0x3d98bdce,
0x3db53d80,0xbdedbd44,0x3d843ddc,0x3cf9bdf8,0x3de23d71,0xbdc63da2,0x3d5bbde7,0xbdf13d2c,0x3dd5bd8e,0x3cc83dfb,0xbdfd3c96,0x3dce3d98,0xbc49bdff,0x3df53d15,0x3dac3dbe,0x3bc9be00,
0xbdb53d80,0x3d44bded,0x3d2c3df1,0xbd5b3de7,0x3da23dc6,0xbd15bdf5,0x3dfdbc96,0x3dce3d98,0x3dfb3cc8,0xbdd5bd8e,0x3bc9be00,0x3dbebdac,0x3de2bd71,0xbdff3c49,0xbdf8bcf9,0xbd84bddc,
0x3db53d80,0x3ded3d44,0x3c963dfd,0x3d98bdce,0x3d153df5,0x3dff3c49,0x3dac3dbe,0x3bc9be00,0x3d8e3dd5,0x3dfbbcc8,0x3df83cf9,0xbd84bddc,0x3dc63da2,0x3de2bd71,0x3df1bd2c,0xbde7bd5b,
0xbb493e00,0xbdb93db1,0xbc173dff,0xbdc23da7,0xbce03dfa,0xbdd83d89,0xbd093df7,0xbddf3d7c,0xbd4f3dea,0xbdef3d38,0xbd663de5,0xbdf33d21,0xbd933dd1,0xbdfc3caf,0xbd9d3dca,0xbdfe3c7b,
0xbc7b3dfe,0x3dcabd9d,0xbd383def,0x3deabd4f,0xbde53d66,0x3df33d21,0xbdfa3ce0,0x3dd83d89,0xbddfbd7c,0x3d093df7,0xbdb9bdb1,0x3b493e00,0xbc17bdff,0xbda73dc2,0x3cafbdfc,0xbdd13d93,
0xbce03dfa,0xbdd83d89,0xbd9d3dca,0xbdfe3c7b,0xbdeabd4f,0xbd38bdef,0xbda7bdc2,0x3c17bdff,0x3d93bdd1,0x3dfcbcaf,0x3ddfbd7c,0x3df73d09,0x3db13db9,0xbb493e00,0x3d213df3,0xbd663de5,
0xbd213df3,0x3de5bd66,0xbdd13d93,0x3dfc3caf,0xbd09bdf7,0xbd7c3ddf,0x3d38bdef,0xbdea3d4f,0x3dc23da7,0xbc17bdff,0x3ce03dfa,0x3d89bdd8,0xbdfebc7b,0x3d9d3dca,0xbdb9bdb1,0x3b493e00,
0xbd4f3dea,0xbdef3d38,0xbdf33d21,0xbde5bd66,0x3d93bdd1,0x3dfcbcaf,0x3dfebc7b,0x3dca3d9d,0xbdb93db1,0xbe00bb49,0xbdffbc17,0xbda7bdc2,0x3dd8bd89,0x3dfa3ce0,0x3df73d09,0x3d7c3ddf,
0xbd7c3ddf,0x3df7bd09,0xbe003b49,0x3db93db1,0x3dffbc17,0xbdc2bda7,0x3d933dd1,0x3cafbdfc,0xbd9dbdca,0xbc7b3dfe,0x3d38bdef,0xbdea3d4f,0xbd213df3,0x3de5bd66,0xbdfa3ce0,0x3dd83d89,
0xbd933dd1,0xbdfc3caf,0xbdf7bd09,0xbd7cbddf,0x3db13db9,0xbb493e00,0xbd663de5,0xbdf33d21,0x3dd8bd89,0x3dfa3ce0,0x3dca3d9d,0x3c7b3dfe,0xbd38bdef,0x3d4fbdea,0x3dc2bda7,0x3dff3c17,
0xbda73dc2,0x3dffbc17,0xbdd8bd89,0x3ce03dfa,0xbc7b3dfe,0x3dcabd9d,0xbe003b49,0x3db93db1,0x3d663de5,0x3d21bdf3,0xbdd13d93,0x3dfc3caf,0x3ddf3d7c,0xbd09bdf7,0xbd383def,0x3deabd4f,
0xbdb93db1,0xbe00bb49,0xbda7bdc2,0x3c17bdff,0xbdd83d89,0xbdfabce0,0xbd7cbddf,0x3d09bdf7,0xbdef3d38,0xbdeabd4f,0xbd21bdf3,0x3d66bde5,0xbdfc3caf,0xbdd1bd93,0xbc7bbdfe,0x3d9dbdca,
0xbdca3d9d,0x3dfe3c7b,0xbd4fbdea,0xbd383def,0xbdf3bd21,0x3d663de5,0x3d89bdd8,0xbdfa3ce0,0xbd09bdf7,0xbd7c3ddf,0x3e00bb49,0xbdb9bdb1,0x3da7bdc2,0xbdff3c17,0x3d933dd1,0x3cafbdfc,
0xbdd83d89,0xbdfabce0,0xbc7bbdfe,0x3d9dbdca,0xbd38bdef,0x3d4fbdea,0x3dff3c17,0x3da73dc2,0x3dfcbcaf,0x3dd13d93,0xbd093df7,0xbddf3d7c,0xbb493e00,0xbdb93db1,0xbde5bd66,0xbd21bdf3,
0xbde53d66,0x3df33d21,0x3cafbdfc,0xbdd13d93,0x3d7cbddf,0xbdf73d09,0x3d4f3dea,0x3d38bdef,0x3c173dff,0x3da7bdc2,0xbdd8bd89,0x3ce03dfa,0xbd9dbdca,0xbc7b3dfe,0x3e00bb49,0xbdb9bdb1,
0xbdef3d38,0xbdeabd4f,0x3d66bde5,0x3df3bd21,0x3dfcbcaf,0x3dd13d93,0xbd9d3dca,0xbdfe3c7b,0xbe00bb49,0xbdb1bdb9,0x3dc2bda7,0x3dff3c17,0x3dfa3ce0,0x3d893dd8,0xbddf3d7c,0xbdf7bd09,
0xbdf73d09,0x3ddf3d7c,0x3db1bdb9,0xbe003b49,0x3dc23da7,0xbc17bdff,0xbdfcbcaf,0x3d933dd1,0x3c7bbdfe,0xbdca3d9d,0x3d4f3dea,0x3d38bdef,0xbde53d66,0x3df33d21,0x3d89bdd8,0xbdfa3ce0,
0xbdfc3caf,0xbdd1bd93,0x3ddfbd7c,0x3df73d09,0xbb493e00,0xbdb93db1,0xbd21bdf3,0x3d66bde5,0x3dfa3ce0,0x3d893dd8,0xbdfe3c7b,0xbdcabd9d,0x3d4fbdea,0x3defbd38,0xbc173dff,0xbdc23da7,
0xbdff3c17,0x3dc23da7,0x3dfabce0,0xbdd8bd89,0xbdca3d9d,0x3dfe3c7b,0x3db1bdb9,0xbe003b49,0xbd213df3,0x3de5bd66,0x3cafbdfc,0xbdd13d93,0x3d093df7,0x3d7cbddf,0xbd4fbdea,0xbd383def,
0xbe00bb49,0xbdb1bdb9,0x3dff3c17,0x3da73dc2,0xbdfabce0,0xbd89bdd8,0x3df73d09,0x3d7c3ddf,0xbdeabd4f,0xbd38bdef,0x3de53d66,0x3d213df3,0xbdd1bd93,0xbcafbdfc,0x3dca3d9d,0x3c7b3dfe,
0xbdfebc7b,0x3d9d3dca,0x3def3d38,0xbd4fbdea,0xbd66bde5,0xbd213df3,0x3ce03dfa,0x3d89bdd8,0x3d7cbddf,0xbdf73d09,0xbdb13db9,0x3e00bb49,0x3dffbc17,0xbdc2bda7,0xbdfcbcaf,0x3d933dd1,
0xbdfabce0,0xbd89bdd8,0x3dca3d9d,0x3c7b3dfe,0x3d4fbdea,0x3defbd38,0xbdc23da7,0xbdffbc17,0x3dd13d93,0x3caf3dfc,0xbd7cbddf,0x3d09bdf7,0xbdb93db1,0xbe00bb49,0x3df3bd21,0x3de53d66,
0xbdf3bd21,0x3d663de5,0x3d933dd1,0x3cafbdfc,0x3df7bd09,0xbddfbd7c,0xbdefbd38,0x3d4f3dea,0xbda73dc2,0x3dffbc17,0x3dfabce0,0xbdd8bd89,0x3c7bbdfe,0xbdca3d9d,0xbdb13db9,0x3e00bb49,
0xbdeabd4f,0xbd38bdef,0x3d213df3,0xbd663de5,0x3dd13d93,0x3caf3dfc,0xbc7bbdfe,0x3d9dbdca,0xbdb1bdb9,0x3b49be00,0xbc173dff,0xbdc23da7,0x3d893dd8,0xbce03dfa,0x3d09bdf7,0x3ddfbd7c,
0xbddfbd7c,0x3d093df7,0x3b493e00,0x3db1bdb9,0x3c173dff,0x3da7bdc2,0x3dd1bd93,0xbdfcbcaf,0x3dcabd9d,0xbdfebc7b,0xbdefbd38,0x3d4f3dea,0xbdf3bd21,0x3d663de5,0x3ce03dfa,0x3d89bdd8,
0xbdd1bd93,0xbcafbdfc,0xbd093df7,0xbddf3d7c,0xbdb93db1,0xbe00bb49,0x3de53d66,0x3d213df3,0x3d893dd8,0xbce03dfa,0x3d9dbdca,0x3dfebc7b,0x3defbd38,0x3dea3d4f,0xbda7bdc2,0x3c17bdff,
0xbdc2bda7,0x3c173dff,0xbd893dd8,0x3dfabce0,0xbdfebc7b,0x3d9d3dca,0x3b493e00,0x3db1bdb9,0xbde53d66,0x3df33d21,0x3d933dd1,0x3cafbdfc,0xbd7c3ddf,0x3df7bd09,0x3def3d38,0xbd4fbdea,
0xbdb1bdb9,0x3b49be00,0xbdc23da7,0xbdffbc17,0xbd89bdd8,0x3ce0bdfa,0xbddf3d7c,0xbdf7bd09,0xbd38bdef,0x3d4fbdea,0xbdf33d21,0xbde5bd66,0xbcafbdfc,0x3d93bdd1,0xbdfe3c7b,0xbdcabd9d,
0xbd9dbdca,0xbc7b3dfe,0xbdea3d4f,0x3def3d38,0x3d21bdf3,0xbde53d66,0xbdd8bd89,0x3ce03dfa,0x3df7bd09,0xbddfbd7c,0xbb49be00,0xbdb13db9,0x3dc23da7,0xbc17bdff,0x3dd1bd93,0xbdfcbcaf,
0xbd89bdd8,0x3ce0bdfa,0xbdfe3c7b,0xbdcabd9d,0x3defbd38,0x3dea3d4f,0x3c17bdff,0x3dc2bda7,0x3caf3dfc,0xbd933dd1,0x3df73d09,0x3d7c3ddf,0xbe00bb49,0xbdb1bdb9,0xbd663de5,0xbdf33d21,
0xbd66bde5,0xbd213df3,0xbdfcbcaf,0x3d933dd1,0x3ddf3d7c,0xbd09bdf7,0x3deabd4f,0xbdefbd38,0xbdff3c17,0x3dc23da7,0xbd893dd8,0x3dfabce0,0x3dcabd9d,0xbdfebc7b,0xbb49be00,0xbdb13db9,
0xbd38bdef,0x3d4fbdea,0xbde5bd66,0xbd21bdf3,0x3caf3dfc,0xbd933dd1,0x3dca3d9d,0x3c7b3dfe,0x3b49be00,0x3db9bdb1,0xbda7bdc2,0x3c17bdff,0xbce03dfa,0xbdd83d89,0x3d7c3ddf,0xbd093df7,
0xbd09bdf7,0xbd7c3ddf,0xbdb9bdb1,0x3b493e00,0xbda73dc2,0x3dffbc17,0xbcaf3dfc,0x3dd1bd93,0x3dfe3c7b,0xbd9dbdca,0x3deabd4f,0xbdefbd38,0xbd66bde5,0xbd213df3,0xbdd8bd89,0x3ce03dfa,
0xbcafbdfc,0x3d93bdd1,0xbd7cbddf,0x3d09bdf7,0xbe00bb49,0xbdb1bdb9,0xbdf33d21,0xbde5bd66,0xbce03dfa,0xbdd83d89,0x3c7b3dfe,0xbd9d3dca,0x3dea3d4f,0x3d383def,0x3dff3c17,0x3da73dc2,
0xbc17bdff,0xbda73dc2,0xbce0bdfa,0xbd893dd8,0xbd9dbdca,0xbc7b3dfe,0xbdb9bdb1,0x3b493e00,0xbdf3bd21,0x3d663de5,0xbdfcbcaf,0x3d933dd1,0xbdf73d09,0x3ddf3d7c,0xbdea3d4f,0x3def3d38,
0xbd803d80,0xbdb53db5,0xbc493dff,0xbdffbc49,0xbcc83dfb,0xbdd53d8e,0xbd713de2,0xbde2bd71,0xbd443ded,0xbded3d44,0xbdc63da2,0xbda2bdc6,0xbd8e3dd5,0xbdfb3cc8,0xbdf53d15,0xbd15bdf5,
0x3d803d80,0xbdb5bdb5,0xbd153df5,0x3df53d15,0xbd8e3dd5,0xbcc8bdfb,0xbdff3c49,0x3c493dff,0xbded3d44,0x3d44bded,0xbd71bde2,0xbde23d71,0xbdfbbcc8,0x3dd5bd8e,0x3da2bdc6,0xbdc6bda2,
0xbd803d80,0x3db5bdb5,0xbd713de2,0xbde2bd71,0xbdd53d8e,0x3dfb3cc8,0xbda2bdc6,0x3dc6bda2,0xbdedbd44,0x3d443ded,0x3df5bd15,0x3d153df5,0xbcc8bdfb,0xbd8e3dd5,0xbc493dff,0xbdffbc49,
0x3d803d80,0x3db53db5,0xbda23dc6,0x3dc63da2,0xbdfb3cc8,0xbd8e3dd5,0x3d15bdf5,0xbdf5bd15,0xbd44bded,0xbdedbd44,0x3c493dff,0x3dffbc49,0x3dd5bd8e,0x3cc8bdfb,0xbd71bde2,0xbde23d71,
0xbd803d80,0xbdb53db5,0xbdc63da2,0xbda2bdc6,0xbdfbbcc8,0xbd8ebdd5,0x3df5bd15,0x3d153df5,0x3d44bded,0x3dedbd44,0xbdffbc49,0x3c49bdff,0x3dd53d8e,0x3cc83dfb,0x3de23d71,0xbd713de2,
0x3d803d80,0xbdb5bdb5,0xbde23d71,0x3d713de2,0xbdd5bd8e,0x3dfbbcc8,0x3dc63da2,0x3da2bdc6,0x3dedbd44,0xbd443ded,0x3d15bdf5,0xbdf5bd15,0xbcc83dfb,0xbd8ebdd5,0xbdff3c49,0x3c493dff,
0xbd803d80,0x3db5bdb5,0xbdf53d15,0xbd15bdf5,0xbd8ebdd5,0xbcc83dfb,0xbc493dff,0xbdffbc49,0x3ded3d44,0xbd44bded,0x3de23d71,0xbd713de2,0xbdfb3cc8,0x3dd53d8e,0x3dc6bda2,0x3da23dc6,
0x3d803d80,0x3db53db5,0xbdff3c49,0x3c493dff,0xbcc8bdfb,0xbdd5bd8e,0xbde23d71,0x3d713de2,0x3d443ded,0x3ded3d44,0xbda23dc6,0x3dc63da2,0xbd8ebdd5,0xbdfbbcc8,0xbd153df5,0x3df53d15,
0xbd803d80,0xbdb53db5,0xbdffbc49,0x3c49bdff,0x3cc8bdfb,0x3dd5bd8e,0xbde2bd71,0x3d71bde2,0xbd443ded,0xbded3d44,0xbda2bdc6,0x3dc6bda2,0x3d8ebdd5,0x3dfbbcc8,0xbd15bdf5,0x3df5bd15,
0x3d803d80,0xbdb5bdb5,0xbdf5bd15,0xbd153df5,0x3d8ebdd5,0x3cc83dfb,0xbc49bdff,0xbdff3c49,0xbded3d44,0x3d44bded,0x3de2bd71,0xbd71bde2,0x3dfb3cc8,0xbdd53d8e,0x3dc63da2,0x3da2bdc6,
0xbd803d80,0x3db5bdb5,0xbde2bd71,0x3d71bde2,0x3dd5bd8e,0xbdfbbcc8,0x3dc6bda2,0x3da23dc6,0xbdedbd44,0x3d443ded,0x3d153df5,0xbdf53d15,0x3cc83dfb,0x3d8ebdd5,0xbdffbc49,0x3c49bdff,
0x3d803d80,0x3db53db5,0xbdc6bda2,0xbda23dc6,0x3dfbbcc8,0x3d8ebdd5,0x3df53d15,0x3d15bdf5,0xbd44bded,0xbdedbd44,0xbdff3c49,0x3c493dff,0xbdd53d8e,0xbcc83dfb,0x3de2bd71,0xbd71bde2,
0xbd803d80,0xbdb53db5,0xbda2bdc6,0x3dc6bda2,0x3dfb3cc8,0x3d8e3dd5,0x3d153df5,0xbdf53d15,0x3d44bded,0x3dedbd44,0x3c49bdff,0x3dff3c49,0xbdd5bd8e,0xbcc8bdfb,0xbd713de2,0xbde2bd71,
0x3d803d80,0xbdb5bdb5,0xbd71bde2,0xbde23d71,0x3dd53d8e,0xbdfb3cc8,0xbda23dc6,0x3dc63da2,0x3dedbd44,0xbd443ded,0x3df53d15,0x3d15bdf5,0x3cc8bdfb,0x3d8e3dd5,0xbc49bdff,0xbdff3c49,
0xbd803d80,0x3db5bdb5,0xbd15bdf5,0x3df5bd15,0x3d8e3dd5,0x3cc8bdfb,0xbdffbc49,0x3c49bdff,0x3ded3d44,0xbd44bded,0xbd713de2,0xbde2bd71,0x3dfbbcc8,0xbdd5bd8e,0x3da23dc6,0xbdc63da2,
0x3d803d80,0x3db53db5,0xbc49bdff,0xbdff3c49,0x3cc83dfb,0x3dd53d8e,0xbd71bde2,0xbde23d71,0x3d443ded,0x3ded3d44,0xbdc6bda2,0xbda23dc6,0x3d8e3dd5,0x3dfb3cc8,0xbdf5bd15,0xbd153df5,
0xbd803d80,0xbdb53db5,0x3c49bdff,0x3dff3c49,0xbcc83dfb,0xbdd53d8e,0x3d71bde2,0x3de23d71,0xbd443ded,0xbded3d44,0x3dc6bda2,0x3da23dc6,0xbd8e3dd5,0xbdfb3cc8,0x3df5bd15,0x3d153df5,
0x3d803d80,0xbdb5bdb5,0x3d15bdf5,0xbdf5bd15,0xbd8e3dd5,0xbcc8bdfb,0x3dffbc49,0xbc49bdff,0xbded3d44,0x3d44bded,0x3d713de2,0x3de2bd71,0xbdfbbcc8,0x3dd5bd8e,0xbda23dc6,0x3dc63da2,
0xbd803d80,0x3db5bdb5,0x3d71bde2,0x3de23d71,0xbdd53d8e,0x3dfb3cc8,0x3da23dc6,0xbdc63da2,0xbdedbd44,0x3d443ded,0xbdf53d15,0xbd15bdf5,0xbcc8bdfb,0xbd8e3dd5,0x3c49bdff,0x3dff3c49,
0x3d803d80,0x3db53db5,0x3da2bdc6,0xbdc6bda2,0xbdfb3cc8,0xbd8e3dd5,0xbd153df5,0x3df53d15,0xbd44bded,0xbdedbd44,0xbc49bdff,0xbdff3c49,0x3dd5bd8e,0x3cc8bdfb,0x3d713de2,0x3de2bd71,
0xbd803d80,0xbdb53db5,0x3dc6bda2,0x3da23dc6,0xbdfbbcc8,0xbd8ebdd5,0xbdf53d15,0xbd15bdf5,0x3d44bded,0x3dedbd44,0x3dff3c49,0xbc493dff,0x3dd53d8e,0x3cc83dfb,0xbde2bd71,0x3d71bde2,
0x3d803d80,0xbdb5bdb5,0x3de2bd71,0xbd71bde2,0xbdd5bd8e,0x3dfbbcc8,0xbdc6bda2,0xbda23dc6,0x3dedbd44,0xbd443ded,0xbd153df5,0x3df53d15,0xbcc83dfb,0xbd8ebdd5,0x3dffbc49,0xbc49bdff,
0xbd803d80,0x3db5bdb5,0x3df5bd15,0x3d153df5,0xbd8ebdd5,0xbcc83dfb,0x3c49bdff,0x3dff3c49,0x3ded3d44,0xbd44bded,0xbde2bd71,0x3d71bde2,0xbdfb3cc8,0x3dd53d8e,0xbdc63da2,0xbda2bdc6,
0x3d803d80,0x3db53db5,0x3dffbc49,0xbc49bdff,0xbcc8bdfb,0xbdd5bd8e,0x3de2bd71,0xbd71bde2,0x3d443ded,0x3ded3d44,0x3da2bdc6,0xbdc6bda2,0xbd8ebdd5,0xbdfbbcc8,0x3d15bdf5,0xbdf5bd15,
0xbd803d80,0xbdb53db5,0x3dff3c49,0xbc493dff,0x3cc8bdfb,0x3dd5bd8e,0x3de23d71,0xbd713de2,0xbd443ded,0xbded3d44,0x3da23dc6,0xbdc63da2,0x3d8ebdd5,0x3dfbbcc8,0x3d153df5,0xbdf53d15,
0x3d803d80,0xbdb5bdb5,0x3df53d15,0x3d15bdf5,0x3d8ebdd5,0x3cc83dfb,0x3c493dff,0x3dffbc49,0xbded3d44,0x3d44bded,0xbde23d71,0x3d713de2,0x3dfb3cc8,0xbdd53d8e,0xbdc6bda2,0xbda23dc6,
0xbd803d80,0x3db5bdb5,0x3de23d71,0xbd713de2,0x3dd5bd8e,0xbdfbbcc8,0xbdc63da2,0xbda2bdc6,0xbdedbd44,0x3d443ded,0xbd15bdf5,0x3df5bd15,0x3cc83dfb,0x3d8ebdd5,0x3dff3c49,0xbc493dff,
0x3d803d80,0x3db53db5,0x3dc63da2,0x3da2bdc6,0x3dfbbcc8,0x3d8ebdd5,0xbdf5bd15,0xbd153df5,0xbd44bded,0xbdedbd44,0x3dffbc49,0xbc49bdff,0xbdd53d8e,0xbcc83dfb,0xbde23d71,0x3d713de2,
0xbd803d80,0xbdb53db5,0x3da23dc6,0xbdc63da2,0x3dfb3cc8,0x3d8e3dd5,0xbd15bdf5,0x3df5bd15,0x3d44bded,0x3dedbd44,0xbc493dff,0xbdffbc49,0xbdd5bd8e,0xbcc8bdfb,0x3d71bde2,0x3de23d71,
0x3d803d80,0xbdb5bdb5,0x3d713de2,0x3de2bd71,0x3dd53d8e,0xbdfb3cc8,0x3da2bdc6,0xbdc6bda2,0x3dedbd44,0xbd443ded,0xbdf5bd15,0xbd153df5,0x3cc8bdfb,0x3d8e3dd5,0x3c493dff,0x3dffbc49,
0xbd803d80,0x3db5bdb5,0x3d153df5,0xbdf53d15,0x3d8e3dd5,0x3cc8bdfb,0x3dff3c49,0xbc493dff,0x3ded3d44,0xbd44bded,0x3d71bde2,0x3de23d71,0x3dfbbcc8,0xbdd5bd8e,0xbda2bdc6,0x3dc6bda2,
0x3d803d80,0x3db53db5,0x3c493dff,0x3dffbc49,0x3cc83dfb,0x3dd53d8e,0x3d713de2,0x3de2bd71,0x3d443ded,0x3ded3d44,0x3dc63da2,0x3da2bdc6,0x3d8e3dd5,0x3dfb3cc8,0x3df53d15,0x3d15bdf5,
0xbbc93e00,0xbe00bbc9,0xbc963dfd,0xbdfdbc96,0xbd5b3de7,0xbde7bd5b,0xbd843ddc,0xbddcbd84,0xbdbe3dac,0xbdacbdbe,0xbdce3d98,0xbd98bdce,0xbdf13d2c,0xbd2cbdf1,0xbdf83cf9,0xbcf9bdf8,
0xbc963dfd,0x3dfd3c96,0xbd5b3de7,0x3de73d5b,0xbdf83cf9,0x3cf93df8,0xbe00bbc9,0xbbc93e00,0xbd98bdce,0xbdce3d98,0xbd2cbdf1,0xbdf13d2c,0x3d84bddc,0xbddcbd84,0x3dbebdac,0xbdacbdbe,
0xbcf93df8,0xbdf8bcf9,0xbdac3dbe,0xbdbebdac,0xbdcebd98,0x3d98bdce,0xbd5bbde7,0x3de7bd5b,0x3ddcbd84,0x3d843ddc,0x3e00bbc9,0x3bc93e00,0x3c963dfd,0xbdfd3c96,0xbd2c3df1,0xbdf1bd2c,
0xbd2c3df1,0x3df13d2c,0xbddc3d84,0x3d843ddc,0xbbc9be00,0xbe003bc9,0x3d98bdce,0xbdcebd98,0x3d5b3de7,0x3de7bd5b,0xbcf93df8,0x3df83cf9,0xbdbebdac,0xbdac3dbe,0xbc96bdfd,0xbdfd3c96,
0xbd5b3de7,0xbde7bd5b,0xbdf83cf9,0xbcf9bdf8,0x3dbebdac,0x3dac3dbe,0x3dfd3c96,0xbc963dfd,0xbdf13d2c,0xbd2cbdf1,0xbddcbd84,0x3d84bddc,0x3e003bc9,0xbbc93e00,0x3d983dce,0xbdce3d98,
0xbd843ddc,0x3ddc3d84,0xbe00bbc9,0xbbc93e00,0x3dfd3c96,0x3c96bdfd,0x3d2c3df1,0x3df1bd2c,0xbcf9bdf8,0xbdf83cf9,0x3dbebdac,0xbdacbdbe,0xbdce3d98,0x3d983dce,0xbde7bd5b,0xbd5b3de7,
0xbd983dce,0xbdcebd98,0xbdf1bd2c,0x3d2cbdf1,0x3d843ddc,0xbddc3d84,0xbdac3dbe,0xbdbebdac,0x3dfdbc96,0x3c963dfd,0x3d5b3de7,0xbde73d5b,0x3cf9bdf8,0x3df83cf9,0x3e00bbc9,0x3bc93e00,
0xbdac3dbe,0x3dbe3dac,0xbdcebd98,0xbd983dce,0xbd2c3df1,0x3df13d2c,0xbdf8bcf9,0xbcf93df8,0x3bc93e00,0x3e00bbc9,0xbdfd3c96,0x3c963dfd,0x3d5b3de7,0x3de7bd5b,0xbddc3d84,0x3d843ddc,
0xbdbe3dac,0xbdacbdbe,0xbd98bdce,0x3dcebd98,0xbdf13d2c,0xbd2cbdf1,0xbcf9bdf8,0x3df8bcf9,0xbe00bbc9,0x3bc9be00,0x3c96bdfd,0x3dfd3c96,0xbde7bd5b,0x3d5bbde7,0x3d84bddc,0x3ddc3d84,
0xbdce3d98,0x3d983dce,0xbd2cbdf1,0xbdf13d2c,0xbddcbd84,0xbd843ddc,0x3dbebdac,0xbdacbdbe,0x3c96bdfd,0xbdfdbc96,0x3de73d5b,0x3d5bbde7,0x3df8bcf9,0xbcf9bdf8,0xbbc93e00,0x3e003bc9,
0xbddc3d84,0xbd84bddc,0xbbc9be00,0x3e00bbc9,0xbc96bdfd,0x3dfdbc96,0x3df13d2c,0xbd2c3df1,0x3df83cf9,0xbcf93df8,0xbdac3dbe,0xbdbebdac,0xbd983dce,0xbdcebd98,0xbd5bbde7,0x3de7bd5b,
0xbde73d5b,0x3d5b3de7,0x3cf9bdf8,0xbdf8bcf9,0x3dacbdbe,0xbdbebdac,0x3c963dfd,0x3dfdbc96,0xbd2c3df1,0x3df13d2c,0xbd84bddc,0xbddc3d84,0xbbc9be00,0xbe003bc9,0x3dce3d98,0x3d98bdce,
0xbdf13d2c,0xbd2cbdf1,0x3d84bddc,0x3ddc3d84,0x3e003bc9,0xbbc93e00,0xbdce3d98,0xbd98bdce,0xbde7bd5b,0x3d5bbde7,0x3df8bcf9,0x3cf93df8,0x3dac3dbe,0xbdbe3dac,0xbdfdbc96,0x3c96bdfd,
0xbdf83cf9,0x3cf93df8,0x3dbebdac,0xbdacbdbe,0x3d983dce,0x3dcebd98,0xbde7bd5b,0xbd5b3de7,0x3d84bddc,0xbddcbd84,0xbbc93e00,0x3e003bc9,0xbdfdbc96,0xbc963dfd,0x3df1bd2c,0xbd2cbdf1,
0xbdfd3c96,0xbc96bdfd,0x3de7bd5b,0x3d5b3de7,0xbcf93df8,0xbdf8bcf9,0xbbc9be00,0x3e00bbc9,0x3dce3d98,0xbd983dce,0xbdf1bd2c,0x3d2cbdf1,0x3ddcbd84,0x3d843ddc,0xbdac3dbe,0xbdbebdac,
0xbe003bc9,0x3bc93e00,0x3dfdbc96,0xbc96bdfd,0xbde73d5b,0x3d5b3de7,0x3ddcbd84,0xbd84bddc,0xbdac3dbe,0x3dbe3dac,0x3d98bdce,0xbdcebd98,0xbd2c3df1,0x3df13d2c,0x3cf9bdf8,0xbdf8bcf9,
0xbe00bbc9,0x3bc9be00,0x3dfd3c96,0xbc963dfd,0xbde7bd5b,0x3d5bbde7,0x3ddc3d84,0xbd843ddc,0xbdacbdbe,0x3dbebdac,0x3d983dce,0xbdce3d98,0xbd2cbdf1,0x3df1bd2c,0x3cf93df8,0xbdf83cf9,
0xbdfdbc96,0xbc963dfd,0x3de73d5b,0x3d5bbde7,0xbcf9bdf8,0xbdf83cf9,0xbbc93e00,0x3e003bc9,0x3dcebd98,0xbd98bdce,0xbdf13d2c,0x3d2c3df1,0x3ddc3d84,0x3d84bddc,0xbdacbdbe,0xbdbe3dac,
0xbdf8bcf9,0x3cf9bdf8,0x3dbe3dac,0xbdac3dbe,0x3d98bdce,0x3dce3d98,0xbde73d5b,0xbd5bbde7,0x3d843ddc,0xbddc3d84,0xbbc9be00,0x3e00bbc9,0xbdfd3c96,0xbc96bdfd,0x3df13d2c,0xbd2c3df1,
0xbdf1bd2c,0xbd2c3df1,0x3d843ddc,0x3ddcbd84,0x3e00bbc9,0xbbc9be00,0xbdcebd98,0xbd983dce,0xbde73d5b,0x3d5b3de7,0x3df83cf9,0x3cf9bdf8,0x3dacbdbe,0xbdbebdac,0xbdfd3c96,0x3c963dfd,
0xbde7bd5b,0x3d5bbde7,0x3cf93df8,0xbdf83cf9,0x3dac3dbe,0xbdbe3dac,0x3c96bdfd,0x3dfd3c96,0xbd2cbdf1,0x3df1bd2c,0xbd843ddc,0xbddcbd84,0xbbc93e00,0xbe00bbc9,0x3dcebd98,0x3d983dce,
0xbddcbd84,0xbd843ddc,0xbbc93e00,0x3e003bc9,0xbc963dfd,0x3dfd3c96,0x3df1bd2c,0xbd2cbdf1,0x3df8bcf9,0xbcf9bdf8,0xbdacbdbe,0xbdbe3dac,0xbd98bdce,0xbdce3d98,0xbd5b3de7,0x3de73d5b,
0xbdcebd98,0x3d98bdce,0xbd2c3df1,0xbdf1bd2c,0xbddc3d84,0xbd84bddc,0x3dbe3dac,0xbdac3dbe,0x3c963dfd,0xbdfd3c96,0x3de7bd5b,0x3d5b3de7,0x3df83cf9,0xbcf93df8,0xbbc9be00,0x3e00bbc9,
0xbdbebdac,0xbdac3dbe,0xbd983dce,0x3dce3d98,0xbdf1bd2c,0xbd2c3df1,0xbcf93df8,0x3df83cf9,0xbe003bc9,0x3bc93e00,0x3c963dfd,0x3dfdbc96,0xbde73d5b,0x3d5b3de7,0x3d843ddc,0x3ddcbd84,
0xbdacbdbe,0x3dbebdac,0xbdce3d98,0xbd98bdce,0xbd2cbdf1,0x3df1bd2c,0xbdf83cf9,0xbcf9bdf8,0x3bc9be00,0x3e003bc9,0xbdfdbc96,0x3c96bdfd,0x3d5bbde7,0x3de73d5b,0xbddcbd84,0x3d84bddc,
0xbd98bdce,0xbdce3d98,0xbdf13d2c,0x3d2c3df1,0x3d84bddc,0xbddcbd84,0xbdacbdbe,0xbdbe3dac,0x3dfd3c96,0x3c96bdfd,0x3d5bbde7,0xbde7bd5b,0x3cf93df8,0x3df8bcf9,0x3e003bc9,0x3bc9be00,
0xbd84bddc,0x3ddcbd84,0xbe003bc9,0xbbc9be00,0x3dfdbc96,0x3c963dfd,0x3d2cbdf1,0x3df13d2c,0xbcf93df8,0xbdf8bcf9,0x3dbe3dac,0xbdac3dbe,0xbdcebd98,0x3d98bdce,0xbde73d5b,0xbd5bbde7,
0xbd5bbde7,0xbde73d5b,0xbdf8bcf9,0xbcf93df8,0x3dbe3dac,0x3dacbdbe,0x3dfdbc96,0xbc96bdfd,0xbdf1bd2c,0xbd2c3df1,0xbddc3d84,0x3d843ddc,0x3e00bbc9,0xbbc9be00,0x3d98bdce,0xbdcebd98,
0xbd2cbdf1,0x3df1bd2c,0xbddcbd84,0x3d84bddc,0xbbc93e00,0xbe00bbc9,0x3d983dce,0xbdce3d98,0x3d5bbde7,0x3de73d5b,0xbcf9bdf8,0x3df8bcf9,0xbdbe3dac,0xbdacbdbe,0xbc963dfd,0xbdfdbc96,
0xbcf9bdf8,0xbdf83cf9,0xbdacbdbe,0xbdbe3dac,0xbdce3d98,0x3d983dce,0xbd5b3de7,0x3de73d5b,0x3ddc3d84,0x3d84bddc,0x3e003bc9,0x3bc9be00,0x3c96bdfd,0xbdfdbc96,0xbd2cbdf1,0xbdf13d2c,
0xbc96bdfd,0x3dfdbc96,0xbd5bbde7,0x3de7bd5b,0xbdf8bcf9,0x3cf9bdf8,0xbe003bc9,0xbbc9be00,0xbd983dce,0xbdcebd98,0xbd2c3df1,0xbdf1bd2c,0x3d843ddc,0xbddc3d84,0x3dbe3dac,0xbdac3dbe,
0xbbc9be00,0xbe003bc9,0xbc96bdfd,0xbdfd3c96,0xbd5bbde7,0xbde73d5b,0xbd84bddc,0xbddc3d84,0xbdbebdac,0xbdac3dbe,0xbdcebd98,0xbd983dce,0xbdf1bd2c,0xbd2c3df1,0xbdf8bcf9,0xbcf93df8,
0xbdb53d80,0xbded3d44,0xbc963dfd,0xbd98bdce,0xbd153df5,0xbdff3c49,0xbdac3dbe,0xbbc9be00,0xbd8e3dd5,0xbdfbbcc8,0xbdf83cf9,0x3d84bddc,0xbdc63da2,0xbde2bd71,0xbdf1bd2c,0x3de7bd5b,
0x3db53d80,0xbd44bded,0xbd2c3df1,0x3d5b3de7,0xbda23dc6,0x3d15bdf5,0xbdfdbc96,0xbdce3d98,0xbdfb3cc8,0x3dd5bd8e,0xbbc9be00,0xbdbebdac,0xbde2bd71,0x3dff3c49,0x3df8bcf9,0x3d84bddc,
0xbdb53d80,0x3dedbd44,0xbd843ddc,0xbcf9bdf8,0xbde23d71,0x3dc63da2,0xbd5bbde7,0x3df13d2c,0xbdd5bd8e,0xbcc83dfb,0x3dfd3c96,0xbdce3d98,0x3c49bdff,0xbdf53d15,0xbdac3dbe,0xbbc9be00,
0x3db53d80,0x3d443ded,0xbdac3dbe,0x3bc93e00,0xbdff3c49,0xbde23d71,0x3d84bddc,0xbcf9bdf8,0xbcc8bdfb,0xbd8ebdd5,0xbd2c3df1,0x3d5b3de7,0x3df5bd15,0x3dc6bda2,0x3c96bdfd,0xbd98bdce,
0xbdb53d80,0xbded3d44,0xbdce3d98,0x3c96bdfd,0xbdf5bd15,0xbc49bdff,0x3e00bbc9,0xbdac3dbe,0x3d8ebdd5,0x3dfb3cc8,0xbddcbd84,0x3df8bcf9,0x3da23dc6,0xbd713de2,0x3d5b3de7,0xbdf1bd2c,
0x3db53d80,0xbd44bded,0xbde73d5b,0xbd2c3df1,0xbdc6bda2,0x3df53d15,0x3d983dce,0x3dfd3c96,0x3dfbbcc8,0xbdd53d8e,0x3dacbdbe,0xbbc9be00,0xbd713de2,0x3c49bdff,0xbddcbd84,0xbdf83cf9,
0xbdb53d80,0x3dedbd44,0xbdf83cf9,0x3d84bddc,0xbd71bde2,0xbda23dc6,0xbd2c3df1,0xbd5bbde7,0x3dd53d8e,0x3cc8bdfb,0x3d983dce,0xbdfdbc96,0xbdffbc49,0x3d153df5,0x3e00bbc9,0xbdac3dbe,
0x3db53d80,0x3d443ded,0xbe003bc9,0xbdac3dbe,0xbc49bdff,0xbd71bde2,0xbdf83cf9,0xbd843ddc,0x3cc83dfb,0x3d8e3dd5,0xbde73d5b,0xbd2c3df1,0xbd15bdf5,0xbda2bdc6,0xbdce3d98,0xbc963dfd,
0xbdb53d80,0xbded3d44,0xbdfdbc96,0x3dcebd98,0x3d15bdf5,0x3dffbc49,0xbdbebdac,0x3e00bbc9,0xbd8e3dd5,0xbdfbbcc8,0xbcf9bdf8,0x3ddc3d84,0x3dc6bda2,0x3de23d71,0x3d2cbdf1,0x3d5b3de7,
0x3db53d80,0xbd44bded,0xbdf1bd2c,0xbde73d5b,0x3da2bdc6,0xbd153df5,0x3c96bdfd,0xbd98bdce,0xbdfb3cc8,0x3dd5bd8e,0x3e00bbc9,0x3dacbdbe,0x3de23d71,0xbdffbc49,0x3cf93df8,0x3ddc3d84,
0xbdb53d80,0x3dedbd44,0xbddcbd84,0x3df8bcf9,0x3de2bd71,0xbdc6bda2,0x3de7bd5b,0xbd2c3df1,0xbdd5bd8e,0xbcc83dfb,0xbc963dfd,0xbd98bdce,0xbc493dff,0x3df5bd15,0xbdbebdac,0x3e00bbc9,
0x3db53d80,0x3d443ded,0xbdbebdac,0xbe003bc9,0x3dffbc49,0x3de2bd71,0x3ddc3d84,0x3df8bcf9,0xbcc8bdfb,0xbd8ebdd5,0xbdf1bd2c,0xbde73d5b,0xbdf53d15,0xbdc63da2,0x3dfd3c96,0x3dcebd98,
0xbdb53d80,0xbded3d44,0xbd98bdce,0x3dfd3c96,0x3df53d15,0x3c493dff,0x3bc93e00,0xbdbebdac,0x3d8ebdd5,0x3dfb3cc8,0x3d84bddc,0x3cf93df8,0xbda2bdc6,0x3d71bde2,0xbde73d5b,0x3d2cbdf1,
0x3db53d80,0xbd44bded,0xbd5bbde7,0xbdf1bd2c,0x3dc63da2,0xbdf5bd15,0xbdce3d98,0xbc963dfd,0x3dfbbcc8,0xbdd53d8e,0x3dbe3dac,0x3e00bbc9,0x3d71bde2,0xbc493dff,0x3d84bddc,0xbcf9bdf8,
0xbdb53d80,0x3dedbd44,0xbcf9bdf8,0x3ddc3d84,0x3d713de2,0x3da2bdc6,0xbdf1bd2c,0x3de7bd5b,0x3dd53d8e,0x3cc8bdfb,0xbdce3d98,0x3c96bdfd,0x3dff3c49,0xbd15bdf5,0x3bc93e00,0xbdbebdac,
0x3db53d80,0x3d443ded,0xbbc9be00,0xbdbebdac,0x3c493dff,0x3d713de2,0xbcf9bdf8,0xbddcbd84,0x3cc83dfb,0x3d8e3dd5,0xbd5bbde7,0xbdf1bd2c,0x3d153df5,0x3da23dc6,0xbd98bdce,0xbdfdbc96,
0xbdb53d80,0xbded3d44,0x3c96bdfd,0x3d983dce,0xbd153df5,0xbdff3c49,0x3dacbdbe,0x3bc93e00,0xbd8e3dd5,0xbdfbbcc8,0x3df8bcf9,0xbd843ddc,0xbdc63da2,0xbde2bd71,0x3df13d2c,0xbde73d5b,
0x3db53d80,0xbd44bded,0x3d2cbdf1,0xbd5bbde7,0xbda23dc6,0x3d15bdf5,0x3dfd3c96,0x3dcebd98,0xbdfb3cc8,0x3dd5bd8e,0x3bc93e00,0x3dbe3dac,0xbde2bd71,0x3dff3c49,0xbdf83cf9,0xbd843ddc,
0xbdb53d80,0x3dedbd44,0x3d84bddc,0x3cf93df8,0xbde23d71,0x3dc63da2,0x3d5b3de7,0xbdf1bd2c,0xbdd5bd8e,0xbcc83dfb,0xbdfdbc96,0x3dcebd98,0x3c49bdff,0xbdf53d15,0x3dacbdbe,0x3bc93e00,
0x3db53d80,0x3d443ded,0x3dacbdbe,0xbbc9be00,0xbdff3c49,0xbde23d71,0xbd843ddc,0x3cf93df8,0xbcc8bdfb,0xbd8ebdd5,0x3d2cbdf1,0xbd5bbde7,0x3df5bd15,0x3dc6bda2,0xbc963dfd,0x3d983dce,
0xbdb53d80,0xbded3d44,0x3dcebd98,0xbc963dfd,0xbdf5bd15,0xbc49bdff,0xbe003bc9,0x3dacbdbe,0x3d8ebdd5,0x3dfb3cc8,0x3ddc3d84,0xbdf83cf9,0x3da23dc6,0xbd713de2,0xbd5bbde7,0x3df13d2c,
0x3db53d80,0xbd44bded,0x3de7bd5b,0x3d2cbdf1,0xbdc6bda2,0x3df53d15,0xbd98bdce,0xbdfdbc96,0x3dfbbcc8,0xbdd53d8e,0xbdac3dbe,0x3bc93e00,0xbd713de2,0x3c49bdff,0x3ddc3d84,0x3df8bcf9,
0xbdb53d80,0x3dedbd44,0x3df8bcf9,0xbd843ddc,0xbd71bde2,0xbda23dc6,0x3d2cbdf1,0x3d5b3de7,0x3dd53d8e,0x3cc8bdfb,0xbd98bdce,0x3dfd3c96,0xbdffbc49,0x3d153df5,0xbe003bc9,0x3dacbdbe,
0x3db53d80,0x3d443ded,0x3e00bbc9,0x3dacbdbe,0xbc49bdff,0xbd71bde2,0x3df8bcf9,0x3d84bddc,0x3cc83dfb,0x3d8e3dd5,0x3de7bd5b,0x3d2cbdf1,0xbd15bdf5,0xbda2bdc6,0x3dcebd98,0x3c96bdfd,
0xbdb53d80,0xbded3d44,0x3dfd3c96,0xbdce3d98,0x3d15bdf5,0x3dffbc49,0x3dbe3dac,0xbe003bc9,0xbd8e3dd5,0xbdfbbcc8,0x3cf93df8,0xbddcbd84,0x3dc6bda2,0x3de23d71,0xbd2c3df1,0xbd5bbde7,
0x3db53d80,0xbd44bded,0x3df13d2c,0x3de7bd5b,0x3da2bdc6,0xbd153df5,0xbc963dfd,0x3d983dce,0xbdfb3cc8,0x3dd5bd8e,0xbe003bc9,0xbdac3dbe,0x3de23d71,0xbdffbc49,0xbcf9bdf8,0xbddcbd84,
0xbdb53d80,0x3dedbd44,0x3ddc3d84,0xbdf83cf9,0x3de2bd71,0xbdc6bda2,0xbde73d5b,0x3d2cbdf1,0xbdd5bd8e,0xbcc83dfb,0x3c96bdfd,0x3d983dce,0xbc493dff,0x3df5bd15,0x3dbe3dac,0xbe003bc9,
0x3db53d80,0x3d443ded,0x3dbe3dac,0x3e00bbc9,0x3dffbc49,0x3de2bd71,0xbddcbd84,0xbdf83cf9,0xbcc8bdfb,0xbd8ebdd5,0x3df13d2c,0x3de7bd5b,0xbdf53d15,0xbdc63da2,0xbdfdbc96,0xbdce3d98,
0xbdb53d80,0xbded3d44,0x3d983dce,0xbdfdbc96,0x3df53d15,0x3c493dff,0xbbc9be00,0x3dbe3dac,0x3d8ebdd5,0x3dfb3cc8,0xbd843ddc,0xbcf9bdf8,0xbda2bdc6,0x3d71bde2,0x3de7bd5b,0xbd2c3df1,
0x3db53d80,0xbd44bded,0x3d5b3de7,0x3df13d2c,0x3dc63da2,0xbdf5bd15,0x3dcebd98,0x3c96bdfd,0x3dfbbcc8,0xbdd53d8e,0xbdbebdac,0xbe003bc9,0x3d71bde2,0xbc493dff,0xbd843ddc,0x3cf93df8,
0xbdb53d80,0x3dedbd44,0x3cf93df8,0xbddcbd84,0x3d713de2,0x3da2bdc6,0x3df13d2c,0xbde73d5b,0x3dd53d8e,0x3cc8bdfb,0x3dcebd98,0xbc963dfd,0x3dff3c49,0xbd15bdf5,0xbbc9be00,0x3dbe3dac,
0x3db53d80,0x3d443ded,0x3bc93e00,0x3dbe3dac,0x3c493dff,0x3d713de2,0x3cf93df8,0x3ddc3d84,0x3cc83dfb,0x3d8e3dd5,0x3d5b3de7,0x3df13d2c,0x3d153df5,0x3da23dc6,0x3d983dce,0x3dfd3c96,
0xbc173dff,0xbda7bdc2,0xbce03dfa,0xbd89bdd8,0xbd9d3dca,0xbc7bbdfe,0xbdb93db1,0x3b49be00,0xbdf33d21,0x3d66bde5,0xbdfc3caf,0x3d93bdd1,0xbdf7bd09,0x3ddfbd7c,0xbdeabd4f,0x3defbd38,
0xbcaf3dfc,0x3d933dd1,0xbd7c3ddf,0x3d093df7,0xbe003b49,0xbdb13db9,0xbdf3bd21,0xbde53d66,0xbce0bdfa,0xbdd8bd89,0x3c7bbdfe,0xbd9dbdca,0x3deabd4f,0x3d38bdef,0x3dffbc17,0x3da7bdc2,
0xbd093df7,0xbd7cbddf,0xbdb93db1,0x3b49be00,0xbda7bdc2,0x3dff3c17,0xbcafbdfc,0x3dd13d93,0x3dfebc7b,0xbd9d3dca,0x3dea3d4f,0xbdef3d38,0xbd663de5,0xbd21bdf3,0xbdd83d89,0x3ce0bdfa,
0xbd383def,0x3d4f3dea,0xbde53d66,0xbd213df3,0x3cafbdfc,0xbd93bdd1,0x3dcabd9d,0x3c7bbdfe,0x3b493e00,0x3db93db1,0xbda73dc2,0x3c173dff,0xbce0bdfa,0xbdd8bd89,0x3d7cbddf,0xbd09bdf7,
0xbd663de5,0xbd21bdf3,0xbdfc3caf,0x3d93bdd1,0x3ddfbd7c,0xbd093df7,0x3dea3d4f,0xbdef3d38,0xbdffbc17,0x3dc2bda7,0xbd89bdd8,0x3dfa3ce0,0x3dca3d9d,0xbdfe3c7b,0xbb493e00,0xbdb1bdb9,
0xbd893dd8,0x3ce03dfa,0xbdfebc7b,0xbdca3d9d,0x3def3d38,0x3deabd4f,0x3c173dff,0x3dc23da7,0x3cafbdfc,0xbd93bdd1,0x3df7bd09,0x3d7cbddf,0xbe003b49,0xbdb13db9,0xbd66bde5,0xbdf3bd21,
0xbd9d3dca,0xbc7bbdfe,0xbdeabd4f,0x3defbd38,0x3d213df3,0xbde5bd66,0xbdd83d89,0x3ce0bdfa,0x3df73d09,0xbddf3d7c,0xbb493e00,0xbdb1bdb9,0x3dc2bda7,0xbc173dff,0x3dd13d93,0xbdfc3caf,
0xbdb13db9,0x3b493e00,0xbdc2bda7,0xbdff3c17,0xbd893dd8,0x3ce03dfa,0xbddfbd7c,0xbdf73d09,0xbd383def,0x3d4f3dea,0xbdf3bd21,0xbde53d66,0xbcaf3dfc,0x3d933dd1,0xbdfebc7b,0xbdca3d9d,
0xbdc23da7,0x3c17bdff,0xbd89bdd8,0x3dfa3ce0,0xbdfe3c7b,0x3d9dbdca,0x3b49be00,0x3db13db9,0xbde5bd66,0x3df3bd21,0x3d93bdd1,0x3caf3dfc,0xbd7cbddf,0x3df73d09,0x3defbd38,0xbd4f3dea,
0xbdd13d93,0xbcaf3dfc,0xbd09bdf7,0xbddfbd7c,0xbdb9bdb1,0xbe003b49,0x3de5bd66,0x3d21bdf3,0x3d89bdd8,0xbce0bdfa,0x3d9d3dca,0x3dfe3c7b,0x3def3d38,0x3deabd4f,0xbda73dc2,0x3c173dff,
0xbddf3d7c,0x3d09bdf7,0x3b49be00,0x3db13db9,0x3c17bdff,0x3da73dc2,0x3dd13d93,0xbdfc3caf,0x3dca3d9d,0xbdfe3c7b,0xbdef3d38,0x3d4fbdea,0xbdf33d21,0x3d66bde5,0x3ce0bdfa,0x3d893dd8,
0xbdea3d4f,0xbd383def,0x3d21bdf3,0xbd66bde5,0x3dd1bd93,0x3cafbdfc,0xbc7b3dfe,0x3d9d3dca,0xbdb13db9,0x3b493e00,0xbc17bdff,0xbdc2bda7,0x3d89bdd8,0xbce0bdfa,0x3d093df7,0x3ddf3d7c,
0xbdf33d21,0x3d66bde5,0x3d93bdd1,0x3caf3dfc,0x3df73d09,0xbddf3d7c,0xbdef3d38,0x3d4fbdea,0xbda7bdc2,0x3dff3c17,0x3dfa3ce0,0xbdd83d89,0x3c7b3dfe,0xbdcabd9d,0xbdb1bdb9,0x3e003b49,
0xbdfa3ce0,0xbd893dd8,0x3dcabd9d,0x3c7bbdfe,0x3d4f3dea,0x3def3d38,0xbdc2bda7,0xbdff3c17,0x3dd1bd93,0x3cafbdfc,0xbd7c3ddf,0x3d093df7,0xbdb9bdb1,0xbe003b49,0x3df33d21,0x3de5bd66,
0xbdfe3c7b,0x3d9dbdca,0x3defbd38,0xbd4f3dea,0xbd663de5,0xbd21bdf3,0x3ce0bdfa,0x3d893dd8,0x3d7c3ddf,0xbdf7bd09,0xbdb1bdb9,0x3e003b49,0x3dff3c17,0xbdc23da7,0xbdfc3caf,0x3d93bdd1,
0xbe003b49,0xbdb13db9,0x3dffbc17,0x3da7bdc2,0xbdfa3ce0,0xbd893dd8,0x3df7bd09,0x3d7cbddf,0xbdea3d4f,0xbd383def,0x3de5bd66,0x3d21bdf3,0xbdd13d93,0xbcaf3dfc,0x3dcabd9d,0x3c7bbdfe,
0xbdffbc17,0x3dc2bda7,0x3dfa3ce0,0xbdd83d89,0xbdcabd9d,0x3dfebc7b,0x3db13db9,0xbe00bb49,0xbd21bdf3,0x3de53d66,0x3caf3dfc,0xbdd1bd93,0x3d09bdf7,0x3d7c3ddf,0xbd4f3dea,0xbd38bdef,
0xbdfcbcaf,0xbdd13d93,0x3ddf3d7c,0x3df7bd09,0xbb49be00,0xbdb9bdb1,0xbd213df3,0x3d663de5,0x3dfabce0,0x3d89bdd8,0xbdfebc7b,0xbdca3d9d,0x3d4f3dea,0x3def3d38,0xbc17bdff,0xbdc2bda7,
0xbdf7bd09,0x3ddfbd7c,0x3db13db9,0xbe00bb49,0x3dc2bda7,0xbc173dff,0xbdfc3caf,0x3d93bdd1,0x3c7b3dfe,0xbdcabd9d,0x3d4fbdea,0x3d383def,0xbde5bd66,0x3df3bd21,0x3d893dd8,0xbdfabce0,
0xbdefbd38,0xbdea3d4f,0x3d663de5,0x3df33d21,0x3dfc3caf,0x3dd1bd93,0xbd9dbdca,0xbdfebc7b,0xbe003b49,0xbdb13db9,0x3dc23da7,0x3dffbc17,0x3dfabce0,0x3d89bdd8,0xbddfbd7c,0xbdf73d09,
0xbde5bd66,0x3df3bd21,0x3caf3dfc,0xbdd1bd93,0x3d7c3ddf,0xbdf7bd09,0x3d4fbdea,0x3d383def,0x3c17bdff,0x3da73dc2,0xbdd83d89,0x3ce0bdfa,0xbd9d3dca,0xbc7bbdfe,0x3e003b49,0xbdb93db1,
0xbdd8bd89,0xbdfa3ce0,0xbc7b3dfe,0x3d9d3dca,0xbd383def,0x3d4f3dea,0x3dffbc17,0x3da7bdc2,0x3dfc3caf,0x3dd1bd93,0xbd09bdf7,0xbddfbd7c,0xbb49be00,0xbdb9bdb1,0xbde53d66,0xbd213df3,
0xbdcabd9d,0x3dfebc7b,0xbd4f3dea,0xbd38bdef,0xbdf33d21,0x3d66bde5,0x3d893dd8,0xbdfabce0,0xbd093df7,0xbd7cbddf,0x3e003b49,0xbdb93db1,0x3da73dc2,0xbdffbc17,0x3d93bdd1,0x3caf3dfc,
0xbdb9bdb1,0xbe003b49,0xbda73dc2,0x3c173dff,0xbdd8bd89,0xbdfa3ce0,0xbd7c3ddf,0x3d093df7,0xbdefbd38,0xbdea3d4f,0xbd213df3,0x3d663de5,0xbdfcbcaf,0xbdd13d93,0xbc7b3dfe,0x3d9d3dca,
0xbda7bdc2,0x3dff3c17,0xbdd83d89,0x3ce0bdfa,0xbc7bbdfe,0x3dca3d9d,0xbe00bb49,0x3db9bdb1,0x3d66bde5,0x3d213df3,0xbdd1bd93,0x3dfcbcaf,0x3ddfbd7c,0xbd093df7,0xbd38bdef,0x3dea3d4f,
0xbd93bdd1,0xbdfcbcaf,0xbdf73d09,0xbd7c3ddf,0x3db1bdb9,0xbb49be00,0xbd66bde5,0xbdf3bd21,0x3dd83d89,0x3dfabce0,0x3dcabd9d,0x3c7bbdfe,0xbd383def,0x3d4f3dea,0x3dc23da7,0x3dffbc17,
0xbd7cbddf,0x3df73d09,0xbe00bb49,0x3db9bdb1,0x3dff3c17,0xbdc23da7,0x3d93bdd1,0x3caf3dfc,0xbd9d3dca,0xbc7bbdfe,0x3d383def,0xbdeabd4f,0xbd21bdf3,0x3de53d66,0xbdfabce0,0x3dd8bd89,
0xbd4fbdea,0xbdefbd38,0xbdf3bd21,0xbde53d66,0x3d933dd1,0x3dfc3caf,0x3dfe3c7b,0x3dcabd9d,0xbdb9bdb1,0xbe003b49,0xbdff3c17,0xbda73dc2,0x3dd83d89,0x3dfabce0,0x3df7bd09,0x3d7cbddf,
0xbd21bdf3,0x3de53d66,0xbdd1bd93,0x3dfcbcaf,0xbd093df7,0xbd7cbddf,0x3d383def,0xbdeabd4f,0x3dc2bda7,0xbc173dff,0x3ce0bdfa,0x3d893dd8,0xbdfe3c7b,0x3d9dbdca,0xbdb93db1,0x3b49be00,
0xbce0bdfa,0xbdd8bd89,0xbd9dbdca,0xbdfebc7b,0xbdea3d4f,0xbd383def,0xbda73dc2,0x3c173dff,0x3d933dd1,0x3dfc3caf,0x3ddf3d7c,0x3df7bd09,0x3db1bdb9,0xbb49be00,0x3d21bdf3,0xbd66bde5,
0xbc7bbdfe,0x3dca3d9d,0xbd38bdef,0x3dea3d4f,0xbde5bd66,0x3df3bd21,0xbdfabce0,0x3dd8bd89,0xbddf3d7c,0x3d09bdf7,0xbdb93db1,0x3b49be00,0xbc173dff,0xbda7bdc2,0x3caf3dfc,0xbdd1bd93,
0xbb49be00,0xbdb9bdb1,0xbc17bdff,0xbdc2bda7,0xbce0bdfa,0xbdd8bd89,0xbd09bdf7,0xbddfbd7c,0xbd4fbdea,0xbdefbd38,0xbd66bde5,0xbdf3bd21,0xbd93bdd1,0xbdfcbcaf,0xbd9dbdca,0xbdfebc7b,
0x3f800000,0x0,0x3f800000,0x0,0x3f800000,0x0,0x3f800000,0x0,0x3f800000,0x0,0x3f800000,0x0,0x3f800000,0x0,0x3f800000,0x0,
0x3f800000,0x0,0x3f7ffb11,0xbc490e90,0x3f7fec43,0xbcc90ab0,0x3f7fd397,0xbd16c32c,0x3f7fb10f,0xbd48fb30,0x3f7f84ab,0xbd7b2b74,0x3f7f4e6d,0xbd96a905,0x3f7f0e58,0xbdafb680,
0x3f800000,0x0,0x3f7fec43,0xbcc90ab0,0x3f7fb10f,0xbd48fb30,0x3f7f4e6d,0xbd96a905,0x3f7ec46d,0xbdc8bd36,0x3f7e1324,0xbdfab273,0x3f7d3aac,0xbe164083,0x3f7c3b28,0xbe2f10a2,
0x3f800000,0x0,0x3f7fd397,0xbd16c32c,0x3f7f4e6d,0xbd96a905,0x3f7e70b0,0xbde1bc2e,0x3f7d3aac,0xbe164083,0x3f7baccd,0xbe3b6ecf,0x3f79c79d,0xbe605c13,0x3f778bc5,0xbe827dc0,
0x3f800000,0x0,0x3f7fb10f,0xbd48fb30,0x3f7ec46d,0xbdc8bd36,0x3f7d3aac,0xbe164083,0x3f7b14be,0xbe47c5c2,0x3f7853f8,0xbe78cfcc,0x3f74fa0b,0xbe94a031,0x3f710908,0xbeac7cd4,
0x3f800000,0x0,0x3f7f84ab,0xbd7b2b74,0x3f7e1324,0xbdfab273,0x3f7baccd,0xbe3b6ecf,0x3f7853f8,0xbe78cfcc,0x3f740bdd,0xbe9aa086,0x3f6ed89e,0xbeb8442a,0x3f68bf3c,0xbed53641,
0x3f800000,0x0,0x3f7f4e6d,0xbd96a905,0x3f7d3aac,0xbe164083,0x3f79c79d,0xbe605c13,0x3f74fa0b,0xbe94a031,0x3f6ed89e,0xbeb8442a,0x3f676bd8,0xbedae880,0x3f5ebe05,0xbefc5d27,
0x3f800000,0x0,0x3f7f0e58,0xbdafb680,0x3f7c3b28,0xbe2f10a2,0x3f778bc5,0xbe827dc0,0x3f710908,0xbeac7cd4,0x3f68bf3c,0xbed53641,0x3f5ebe05,0xbefc5d27,0x3f531849,0xbf10d3cd,
0x3f800000,0x0,0x3f7b14be,0xbe47c5c2,0x3f6c835e,0xbec3ef15,0x3f54db31,0xbf0e39da,0x3f3504f3,0xbf3504f3,0x3f0e39da,0xbf54db31,0x3ec3ef15,0xbf6c835e,0x3e47c5c2,0xbf7b14be,
0x3f800000,0x0,0x3f7a7302,0xbe541501,0x3f6a09a7,0xbecf7bca,0x3f4f7a1f,0xbf15f6d9,0x3f2beb4a,0xbf3daef9,0x3f00e7e4,0xbf5d2d53,0x3ea09ae5,0xbf731447,0x3de1bc2e,0xbf7e70b0,
0x3f800000,0x0,0x3f79c79d,0xbe605c13,0x3f676bd8,0xbedae880,0x3f49d112,0xbf1d7fd1,0x3f226799,0xbf45e403,0x3ee63375,0xbf64aa59,0x3e78cfcc,0xbf7853f8,0x3cc90ab0,0xbf7fec43,
0x3f800000,0x0,0x3f791298,0xbe6c9a7f,0x3f64aa59,0xbee63375,0x3f43e200,0xbf24d225,0x3f187fc0,0xbf4d9f02,0x3ec9b953,0xbf6b4b0c,0x3e2f10a2,0xbf7c3b28,0xbd7b2b74,0xbf7f84ab,
0x3f800000,0x0,0x3f7853f8,0xbe78cfcc,0x3f61c598,0xbef15aea,0x3f3daef9,0xbf2beb4a,0x3f0e39da,0xbf54db31,0x3eac7cd4,0xbf710908,0x3dc8bd36,0xbf7ec46d,0xbe164083,0xbf7d3aac,
0x3f800000,0x0,0x3f778bc5,0xbe827dc0,0x3f5ebe05,0xbefc5d27,0x3f373a23,0xbf32c8c9,0x3f039c3d,0xbf5b941a,0x3e8e9a22,0xbf75dec6,0x3cc90ab0,0xbf7fec43,0xbe6c9a7f,0xbf791298,
0x3f800000,0x0,0x3f76ba07,0xbe888e93,0x3f5b941a,0xbf039c3d,0x3f3085bb,0xbf396842,0x3ef15aea,0xbf61c598,0x3e605c13,0xbf79c79d,0xbd48fb30,0xbf7fb10f,0xbea09ae5,0xbf731447,
0x3f800000,0x0,0x3f75dec6,0xbe8e9a22,0x3f584853,0xbf08f59b,0x3f299415,0xbf3fc767,0x3edae880,0xbf676bd8,0x3e22abb6,0xbf7cbfc9,0xbdfab273,0xbf7e1324,0xbec9b953,0xbf6b4b0c,
0x3f800000,0x0,0x3f7ec46d,0xbdc8bd36,0x3f7b14be,0xbe47c5c2,0x3f74fa0b,0xbe94a031,0x3f6c835e,0xbec3ef15,0x3f61c598,0xbef15aea,0x3f54db31,0xbf0e39da,0x3f45e403,0xbf226799,
0x3f800000,0x0,0x3f6b4b0c,0xbec9b953,0x3f3085bb,0xbf396842,0x3eb263ef,0xbf6ff573,0xbd48fb30,0xbf7fb10f,0xbee0924f,0xbf660f88,0xbf41d870,0xbf273656,0xbf740bdd,0xbe9aa086,
0x3f800000,0x0,0x3f6a09a7,0xbecf7bca,0x3f2beb4a,0xbf3daef9,0x3ea09ae5,0xbf731447,0xbdc8bd36,0xbf7ec46d,0xbefc5d27,0xbf5ebe05,0xbf4d9f02,0xbf187fc0,0xbf79c79d,0xbe605c13,
0x3f800000,0x0,0x3f68bf3c,0xbed53641,0x3f273656,0xbf41d870,0x3e8e9a22,0xbf75dec6,0xbe164083,0xbf7d3aac,0xbf0b9a6b,0xbf5695e5,0xbf584853,0xbf08f59b,0xbf7dabcc,0xbe09cf86,
0x3f800000,0x0,0x3f676bd8,0xbedae880,0x3f226799,0xbf45e403,0x3e78cfcc,0xbf7853f8,0xbe47c5c2,0xbf7b14be,0xbf187fc0,0xbf4d9f02,0xbf61c598,0xbef15aea,0xbf7fb10f,0xbd48fb30,
0x3f800000,0x0,0x3f660f88,0xbee0924f,0x3f1d7fd1,0xbf49d112,0x3e541501,0xbf7a7302,0xbe78cfcc,0xbf7853f8,0xbf24d225,0xbf43e200,0xbf6a09a7,0xbecf7bca,0xbf7fd397,0x3d16c32c,
0x3f800000,0x0,0x3f64aa59,0xbee63375,0x3f187fc0,0xbf4d9f02,0x3e2f10a2,0xbf7c3b28,0xbe94a031,0xbf74fa0b,0xbf3085bb,0xbf396842,0xbf710908,0xbeac7cd4,0xbf7e1324,0x3dfab273,
0x3f800000,0x0,0x3f633c5a,0xbeebcbbb,0x3f13682a,0xbf514d3d,0x3e09cf86,0xbf7dabcc,0xbeac7cd4,0xbf710908,0xbf3b8f3b,0xbf2e3bde,0xbf76ba07,0xbe888e93,0xbf7a7302,0x3e541501,
0x3f800000,0x0,0x3f74fa0b,0xbe94a031,0x3f54db31,0xbf0e39da,0x3f226799,0xbf45e403,0x3ec3ef15,0xbf6c835e,0x3dc8bd36,0xbf7ec46d,0xbe47c5c2,0xbf7b14be,0xbef15aea,0xbf61c598,
0x3f800000,0x0,0x3f531849,0xbf10d3cd,0x3eb8442a,0xbf6ed89e,0xbe6c9a7f,0xbf791298,0xbf3daef9,0xbf2beb4a,0xbf7dabcc,0xbe09cf86,0xbf64aa59,0x3ee63375,0xbef6e0cb,0x3f604621,
0x3f800000,0x0,0x3f514d3d,0xbf13682a,0x3eac7cd4,0xbf710908,0xbe888e93,0xbf76ba07,0xbf45e403,0xbf226799,0xbf7f4e6d,0xbd96a905,0xbf5b941a,0x3f039c3d,0xbecf7bca,0x3f6a09a7,
0x3f800000,0x0,0x3f4f7a1f,0xbf15f6d9,0x3ea09ae5,0xbf731447,0xbe9aa086,0xbf740bdd,0xbf4d9f02,0xbf187fc0,0xbf7ffb11,0xbc490e90,0xbf514d3d,0x3f13682a,0xbea68f12,0x3f721352,
0x3f800000,0x0,0x3f4d9f02,0xbf187fc0,0x3e94a031,0xbf74fa0b,0xbeac7cd4,0xbf710908,0xbf54db31,0xbf0e39da,0xbf7fb10f,0x3d48fb30,0xbf45e403,0x3f226799,0xbe78cfcc,0x3f7853f8,
0x3f800000,0x0,0x3f4bbbf8,0xbf1b02c6,0x3e888e93,0xbf76ba07,0xbebe1d4a,0xbf6db293,0xbf5b941a,0xbf039c3d,0xbf7e70b0,0x3de1bc2e,0xbf396842,0x3f3085bb,0xbe22abb6,0x3f7cbfc9,
0x3f800000,0x0,0x3f49d112,0xbf1d7fd1,0x3e78cfcc,0xbf7853f8,0xbecf7bca,0xbf6a09a7,0xbf61c598,0xbef15aea,0xbf7c3b28,0x3e2f10a2,0xbf2beb4a,0x3f3daef9,0xbd96a905,0x3f7f4e6d,
0x3f800000,0x0,0x3f47de65,0xbf1ff6cb,0x3e605c13,0xbf79c79d,0xbee0924f,0xbf660f88,0xbf676bd8,0xbedae880,0xbf791298,0x3e6c9a7f,0xbf1d7fd1,0x3f49d112,0x3c490e90,0x3f7ffb11,
0x3f800000,0x0,0x3f800000,0x0,0x3f800000,0x0,0x3f800000,0x0,0x40000000,0x0,0x3f800000,0x0,0x3f800000,0x0,0x3f800000,0x0,
0x3f800000,0x0,0x3f7ffb11,0xbc490e90,0x3f7fec43,0xbcc90ab0,0x3f7fd397,0xbd16c32c,0x3fffb10f,0xbdc8fb30,0x3f7f84ab,0xbd7b2b74,0x3f7f4e6d,0xbd96a905,0x3f7f0e58,0xbdafb680,
0x3f800000,0x0,0x3f7fec43,0xbcc90ab0,0x3f7fb10f,0xbd48fb30,0x3f7f4e6d,0xbd96a905,0x3ffec46d,0xbe48bd36,0x3f7e1324,0xbdfab273,0x3f7d3aac,0xbe164083,0x3f7c3b28,0xbe2f10a2,
0x3f800000,0x0,0x3f7fd397,0xbd16c32c,0x3f7f4e6d,0xbd96a905,0x3f7e70b0,0xbde1bc2e,0x3ffd3aac,0xbe964083,0x3f7baccd,0xbe3b6ecf,0x3f79c79d,0xbe605c13,0x3f778bc5,0xbe827dc0,
0x3f800000,0x0,0x3f7fb10f,0xbd48fb30,0x3f7ec46d,0xbdc8bd36,0x3f7d3aac,0xbe164083,0x3ffb14be,0xbec7c5c2,0x3f7853f8,0xbe78cfcc,0x3f74fa0b,0xbe94a031,0x3f710908,0xbeac7cd4,
0x3f800000,0x0,0x3f7f84ab,0xbd7b2b74,0x3f7e1324,0xbdfab273,0x3f7baccd,0xbe3b6ecf,0x3ff853f8,0xbef8cfcc,0x3f740bdd,0xbe9aa086,0x3f6ed89e,0xbeb8442a,0x3f68bf3c,0xbed53641,
0x3f800000,0x0,0x3f7f4e6d,0xbd96a905,0x3f7d3aac,0xbe164083,0x3f79c79d,0xbe605c13,0x3ff4fa0b,0xbf14a031,0x3f6ed89e,0xbeb8442a,0x3f676bd8,0xbedae880,0x3f5ebe05,0xbefc5d27,
0x3f800000,0x0,0x3f7f0e58,0xbdafb680,0x3f7c3b28,0xbe2f10a2,0x3f778bc5,0xbe827dc0,0x3ff10908,0xbf2c7cd4,0x3f68bf3c,0xbed53641,0x3f5ebe05,0xbefc5d27,0x3f531849,0xbf10d3cd,
0x3f800000,0x0,0x3f7ec46d,0xbdc8bd36,0x3f7b14be,0xbe47c5c2,0x3f74fa0b,0xbe94a031,0x3fec835e,0xbf43ef15,0x3f61c598,0xbef15aea,0x3f54db31,0xbf0e39da,0x3f45e403,0xbf226799,
0x3f800000,0x0,0x3f7e70b0,0xbde1bc2e,0x3f79c79d,0xbe605c13,0x3f721352,0xbea68f12,0x3fe76bd8,0xbf5ae880,0x3f59f26a,0xbf064b82,0x3f49d112,0xbf1d7fd1,0x3f373a23,0xbf32c8c9,
0x3f800000,0x0,0x3f7e1324,0xbdfab273,0x3f7853f8,0xbe78cfcc,0x3f6ed89e,0xbeb8442a,0x3fe1c598,0xbf715aea,0x3f514d3d,0xbf13682a,0x3f3daef9,0xbf2beb4a,0x3f273656,0xbf41d870,
0x3f800000,0x0,0x3f7dabcc,0xbe09cf86,0x3f76ba07,0xbe888e93,0x3f6b4b0c,0xbec9b953,0x3fdb941a,0xbf839c3d,0x3f47de65,0xbf1ff6cb,0x3f3085bb,0xbf396842,0x3f15f6d9,0xbf4f7a1f,
0x3f800000,0x0,0x3f7d3aac,0xbe164083,0x3f74fa0b,0xbe94a031,0x3f676bd8,0xbedae880,0x3fd4db31,0xbf8e39da,0x3f3daef9,0xbf2beb4a,0x3f226799,0xbf45e403,0x3f039c3d,0xbf5b941a,
0x3f800000,0x0,0x3f7cbfc9,0xbe22abb6,0x3f731447,0xbea09ae5,0x3f633c5a,0xbeebcbbb,0x3fcd9f02,0xbf987fc0,0x3f32c8c9,0xbf373a23,0x3f13682a,0xbf514d3d,0x3ee0924f,0xbf660f88,
0x3f800000,0x0,0x3f7c3b28,0xbe2f10a2,0x3f710908,0xbeac7cd4,0x3f5ebe05,0xbefc5d27,0x3fc5e403,0xbfa26799,0x3f273656,0xbf41d870,0x3f039c3d,0xbf5b941a,0x3eb8442a,0xbf6ed89e,
0x3f800000,0x0,0x3f7baccd,0xbe3b6ecf,0x3f6ed89e,0xbeb8442a,0x3f59f26a,0xbf064b82,0x3fbdaef9,0xbfabeb4a,0x3f1b02c6,0xbf4bbbf8,0x3ee63375,0xbf64aa59,0x3e8e9a22,0xbf75dec6,
0x3f800000,0x0,0x3f7b14be,0xbe47c5c2,0x3f6c835e,0xbec3ef15,0x3f54db31,0xbf0e39da,0x3fb504f3,0xbfb504f3,0x3f0e39da,0xbf54db31,0x3ec3ef15,0xbf6c835e,0x3e47c5c2,0xbf7b14be,
0x3f800000,0x0,0x3f7a7302,0xbe541501,0x3f6a09a7,0xbecf7bca,0x3f4f7a1f,0xbf15f6d9,0x3fabeb4a,0xbfbdaef9,0x3f00e7e4,0xbf5d2d53,0x3ea09ae5,0xbf731447,0x3de1bc2e,0xbf7e70b0,
0x3f800000,0x0,0x3f79c79d,0xbe605c13,0x3f676bd8,0xbedae880,0x3f49d112,0xbf1d7fd1,0x3fa26799,0xbfc5e403,0x3ee63375,0xbf64aa59,0x3e78cfcc,0xbf7853f8,0x3cc90ab0,0xbf7fec43,
0x3f800000,0x0,0x3f791298,0xbe6c9a7f,0x3f64aa59,0xbee63375,0x3f43e200,0xbf24d225,0x3f987fc0,0xbfcd9f02,0x3ec9b953,0xbf6b4b0c,0x3e2f10a2,0xbf7c3b28,0xbd7b2b74,0xbf7f84ab,
0x3f800000,0x0,0x3f7853f8,0xbe78cfcc,0x3f61c598,0xbef15aea,0x3f3daef9,0xbf2beb4a,0x3f8e39da,0xbfd4db31,0x3eac7cd4,0xbf710908,0x3dc8bd36,0xbf7ec46d,0xbe164083,0xbf7d3aac,
0x3f800000,0x0,0x3f778bc5,0xbe827dc0,0x3f5ebe05,0xbefc5d27,0x3f373a23,0xbf32c8c9,0x3f839c3d,0xbfdb941a,0x3e8e9a22,0xbf75dec6,0x3cc90ab0,0xbf7fec43,0xbe6c9a7f,0xbf791298,
0x3f800000,0x0,0x3f76ba07,0xbe888e93,0x3f5b941a,0xbf039c3d,0x3f3085bb,0xbf396842,0x3f715aea,0xbfe1c598,0x3e605c13,0xbf79c79d,0xbd48fb30,0xbf7fb10f,0xbea09ae5,0xbf731447,
0x3f800000,0x0,0x3f75dec6,0xbe8e9a22,0x3f584853,0xbf08f59b,0x3f299415,0xbf3fc767,0x3f5ae880,0xbfe76bd8,0x3e22abb6,0xbf7cbfc9,0xbdfab273,0xbf7e1324,0xbec9b953,0xbf6b4b0c,
0x3f800000,0x0,0x3f74fa0b,0xbe94a031,0x3f54db31,0xbf0e39da,0x3f226799,0xbf45e403,0x3f43ef15,0xbfec835e,0x3dc8bd36,0xbf7ec46d,0xbe47c5c2,0xbf7b14be,0xbef15aea,0xbf61c598,
0x3f800000,0x0,0x3f740bdd,0xbe9aa086,0x3f514d3d,0xbf13682a,0x3f1b02c6,0xbf4bbbf8,0x3f2c7cd4,0xbff10908,0x3d16c32c,0xbf7fd397,0xbe888e93,0xbf76ba07,0xbf0b9a6b,0xbf5695e5,
0x3f800000,0x0,0x3f731447,0xbea09ae5,0x3f4d9f02,0xbf187fc0,0x3f13682a,0xbf514d3d,0x3f14a031,0xbff4fa0b,0xbcc90ab0,0xbf7fec43,0xbeac7cd4,0xbf710908,0xbf1d7fd1,0xbf49d112,
0x3f800000,0x0,0x3f721352,0xbea68f12,0x3f49d112,0xbf1d7fd1,0x3f0b9a6b,0xbf5695e5,0x3ef8cfcc,0xbff853f8,0xbdafb680,0xbf7f0e58,0xbecf7bca,0xbf6a09a7,0xbf2e3bde,0xbf3b8f3b,
0x3f800000,0x0,0x3f710908,0xbeac7cd4,0x3f45e403,0xbf226799,0x3f039c3d,0xbf5b941a,0x3ec7c5c2,0xbffb14be,0xbe164083,0xbf7d3aac,0xbef15aea,0xbf61c598,0xbf3daef9,0xbf2beb4a,
0x3f800000,0x0,0x3f6ff573,0xbeb263ef,0x3f41d870,0xbf273656,0x3ef6e0cb,0xbf604621,0x3e964083,0xbffd3aac,0xbe541501,0xbf7a7302,0xbf08f59b,0xbf584853,0xbf4bbbf8,0xbf1b02c6,
0x3f800000,0x0,0x3f6ed89e,0xbeb8442a,0x3f3daef9,0xbf2beb4a,0x3ee63375,0xbf64aa59,0x3e48bd36,0xbffec46d,0xbe888e93,0xbf76ba07,0xbf187fc0,0xbf4d9f02,0xbf584853,0xbf08f59b,
0x3f800000,0x0,0x3f6db293,0xbebe1d4a,0x3f396842,0xbf3085bb,0x3ed53641,0xbf68bf3c,0x3dc8fb30,0xbfffb10f,0xbea68f12,0xbf721352,0xbf273656,0xbf41d870,0xbf633c5a,0xbeebcbbb,
0x3f800000,0x0,0x3f7fffb1,0xbb490fc6,0x3f7ffec4,0xbbc90f88,0x3f7ffd39,0xbc16cb58,0x3ffffb11,0xbcc90e90,0x3f7ff84a,0xbc7b514b,0x3f7ff4e6,0xbc96c9b6,0x3f7ff0e3,0xbcafea69,
0x3f800000,0x0,0x3f7ff84a,0xbc7b514b,0x3f7fe129,0xbcfb49ba,0x3f7fba9e,0xbd3c6dd5,0x3fff84ab,0xbdfb2b74,0x3f7f3f54,0xbd9cecf9,0x3f7eea9d,0xbdbc3ac3,0x3f7e868b,0xbddb7d37,
0x3f800000,0x0,0x3f7fe705,0xbce22a7a,0x3f7f9c18,0xbd621469,0x3f7f1f49,0xbda973ba,0x3ffe70b0,0xbe61bc2e,0x3f7d906e,0xbe0cec4a,0x3f7c7eb0,0xbe28defc,0x3f7b3bab,0xbe44b0b9,
0x3f800000,0x0,0x3f7fcbe2,0xbd2351cb,0x3f7f2f9d,0xbda3308c,0x3f7e2b72,0xbdf475c0,0x3ffcbfc9,0xbea2abb6,0x3f7aed37,0xbe4ada4f,0x3f78b47b,0xbe72b651,0x3f76167a,0xbe8d17c0,
0x3f800000,0x0,0x3f7fa6e3,0xbd55880e,0x3f7e9bc9,0xbdd53db9,0x3f7cdf6c,0xbe1f917b,0x3ffa7302,0xbed41501,0x3f77583a,0xbe840270,0x3f73913f,0xbe9d9e78,0x3f6f20b0,0xbeb6ccc3,
0x3f800000,0x0,0x3f7f7808,0xbd83db0a,0x3f7de0b1,0xbe039502,0x3f7b3bab,0xbe44b0b9,0x3ff78bc5,0xbf027dc0,0x3f72d4eb,0xbea21887,0x3f6d1c1d,0xbec1071e,0x3f666771,0xbedf28a9,
0x3f800000,0x0,0x3f7f3f54,0xbd9cecf9,0x3f7cfe73,0xbe1c76de,0x3f7940c0,0xbe698bba,0x3ff40bdd,0xbf1aa086,0x3f6d67a1,0xbebf926f,0x3f655e0b,0xbee363fa,0x3f5bfb34,0xbf02ef9f,
0x3f800000,0x0,0x3f7efcc9,0xbdb5f8da,0x3f7bf531,0xbe354098,0x3f76ef5b,0xbe870ada,0x3feff573,0xbf3263ef,0x3f671599,0xbedc53c1,0x3f5c61c7,0xbf0242b1,0x3f4fefa8,0xbf1553b7,
0x3f800000,0x0,0x3f7eb069,0xbdcefdb7,0x3f7ac516,0xbe4dee60,0x3f74484b,0xbe9920fe,0x3feb4b0c,0xbf49b953,0x3f5fe4e9,0xbef840c8,0x3f5233c6,0xbf121eb0,0x3f425b89,0xbf269de3,
0x3f800000,0x0,0x3f7e5a38,0xbde7fa9a,0x3f796e4e,0xbe667c66,0x3f714c7a,0xbeab0201,0x3fe60f88,0xbf60924f,0x3f57dc7f,0xbf099f4e,0x3f46e22a,0xbf212ff9,0x3f33587a,0xbf36ad7f,
0x3f800000,0x0,0x3f7dfa38,0xbe007745,0x3f77f110,0xbe7ee6e1,0x3f6dfcf2,0xbebca7af,0x3fe04621,0xbf76e0cb,0x3f4f0417,0xbf16999f,0x3f3a7ca4,0xbf2f61a5,0x3f2302d3,0xbf456439,
0x3f800000,0x0,0x3f7d906e,0xbe0cec4a,0x3f764d97,0xbe8b9507,0x3f6a5ad9,0xbece0bea,0x3fd9f26a,0xbf864b82,0x3f456439,0xbf2302d3,0x3f2d1469,0xbf3ca003,0x3f11796b,0xbf52a649,
0x3f800000,0x0,0x3f7d1cdd,0xbe195be0,0x3f748422,0xbe97a117,0x3f666771,0xbedf28a9,0x3fd31849,0xbf90d3cd,0x3f3b0629,0xbf2ecef7,0x3f1ebc12,0xbf48d8b3,0x3efdbabb,0xbf5e5aa6,
0x3f800000,0x0,0x3f7c9f8a,0xbe25c58c,0x3f7294f8,0xbea395c5,0x3f62241a,0xbeeff7fb,0x3fcbbbf8,0xbf9b02c6,0x3f2ff3e6,0xbf39f2ac,0x3f0f8784,0xbf53fac3,0x3ed6a399,0xbf686b39,
0x3f800000,0x0,0x3f7c187a,0xbe3228d4,0x3f708066,0xbeaf713a,0x3f5d924d,0xbf003a06,0x3fc3e200,0xbfa4d225,0x3f24381a,0xbf446337,0x3eff17b2,0xbf5df6be,0x3eadf73c,0xbf70c501,
0x3f800000,0x0,0x3f7b87b2,0xbe3e853e,0x3f6e46be,0xbebb31a0,0x3f58b3a1,0xbf084b92,0x3fbb8f3b,0xbfae3bde,0x3f17de12,0xbf4e1689,0x3eddbe79,0xbf66becc,0x3e840270,0xbf77583a,
0x3f800000,0x0,0x3f7aed37,0xbe4ada4f,0x3f6be858,0xbec6d529,0x3f5389c7,0xbf102dd5,0x3fb2c8c9,0xbfb73a23,0x3f0af1b7,0xbf570348,0x3ebb31a0,0xbf6e46be,0x3e3228d4,0xbf7c187a,
0x3f800000,0x0,0x3f7a4910,0xbe57278f,0x3f696591,0xbed25a09,0x3f4e1689,0xbf17de12,0x3fa99415,0xbfbfc767,0x3efafef7,0xbf5f20db,0x3e97a117,0xbf748422,0x3db5f8da,0xbf7efcc9,
0x3f800000,0x0,0x3f799b43,0xbe636c83,0x3f66becc,0xbeddbe79,0x3f485bca,0xbf1f599f,0x3f9ff6cb,0xbfc7de65,0x3edf28a9,0xbf666771,0x3e667c66,0xbf796e4e,0x3b490fc6,0xbf7fffb1,
0x3f800000,0x0,0x3f78e3d6,0xbe6fa8b2,0x3f63f473,0xbee900b7,0x3f425b89,0xbf269de3,0x3f95f6d9,0xbfcf7a1f,0x3ec27b55,0xbf6cd007,0x3e1c76de,0xbf7cfe73,0xbda973ba,0xbf7f1f49,
0x3f800000,0x0,0x3f7822d1,0xbe7bdba4,0x3f6106f2,0xbef41f07,0x3f3c17d9,0xbf2da859,0x3f8b9a6b,0xbfd695e5,0x3ea5129f,0xbf725470,0x3da3308c,0xbf7f2f9d,0xbe2bf804,0xbf7c5d3a,
0x3f800000,0x0,0x3f77583a,0xbe840270,0x3f5df6be,0xbeff17b2,0x3f3592e7,0xbf34768f,0x3f80e7e4,0xbfdd2d53,0x3e870ada,0xbf76ef5b,0x3bc90f88,0xbf7ffec4,0xbe80f8c0,0xbf77beb7,
0x3f800000,0x0,0x3f76841b,0xbe8a11f7,0x3f5ac450,0xbf04f484,0x3f2ecef7,0xbf3b0629,0x3f6bcbbb,0xbfe33c5a,0x3e5101f1,0xbf7a9c59,0xbd8a200a,0xbf7f6ac7,0xbeab0201,0xbf714c7a,
0x3f800000,0x0,0x3f75a67b,0xbe901c2c,0x3f577026,0xbf0a48ad,0x3f27ce61,0xbf4154e1,0x3f553641,0xbfe8bf3c,0x3e1324ca,0xbf7d57de,0xbe1008b7,0xbf7d7474,0xbed3c867,0xbf6912ae,
0x3f800000,0x0,0x3f74bf62,0xbe9620d2,0x3f53fac3,0xbf0f8784,0x3f209393,0xbf476085,0x3f3e1d4a,0xbfedb293,0x3da973ba,0xbf7f1f49,0xbe5a3997,0xbf7a1e84,0xbefafef7,0xbf5f20db,
0x3f800000,0x0,0x3f73ced9,0xbe9c1faf,0x3f5064af,0xbf14b039,0x3f19210f,0xbf4d26fd,0x3f268f12,0xbff21352,0x3cafea69,0xbf7ff0e3,0xbe919ddd,0xbf756d97,0xbf102dd5,0xbf5389c7,
0x3f800000,0x0,0x3f72d4eb,0xbea21887,0x3f4cae79,0xbf19c200,0x3f11796b,0xbf52a649,0x3f0e9a22,0xbff5dec6,0xbd2351cb,0xbf7fcbe2,0xbeb554ec,0xbf6f6830,0xbf21cbfb,0xbf466354,
0x3f800000,0x0,0x3f71d19f,0xbea80b1f,0x3f48d8b3,0xbf1ebc12,0x3f099f4e,0xbf57dc7f,0x3eec9a7f,0xbff91298,0xbdcefdb7,0xbf7eb069,0xbed8106b,0xbf6816a8,0xbf3238aa,0xbf37c655,
0x3f800000,0x0,0x3f70c501,0xbeadf73c,0x3f44e3f5,0xbf239da9,0x3f019573,0xbf5cc7d1,0x3ebb6ecf,0xbffbaccd,0xbe25c58c,0xbf7c9f8a,0xbef9a02d,0xbf5f8327,0xbf4154e1,0xbf27ce61,
0x3f800000,0x0,0x3f6faf1b,0xbeb3dca5,0x3f40d0da,0xbf286605,0x3ef2bd43,0xbf61668a,0x3e89cf86,0xbffdabcc,0xbe636c83,0xbf799b43,0xbf0cead0,0xbf55b993,0xbf4f0417,0xbf16999f,
0x3f800000,0x0,0x3f6e8ff8,0xbeb9bb1e,0x3f3ca003,0xbf2d1469,0x3ee1fb6a,0xbf65b710,0x3e2fb680,0xbfff0e58,0xbe901c2c,0xbf75a67b,0xbf1c420c,0xbf4ac77f,0xbf5b2c79,0xbf044889,
0x3f800000,0x0,0x3f6d67a1,0xbebf926f,0x3f385216,0xbf31a81d,0x3ed0eb2a,0xbf69b7e4,0x3d96c32c,0xbfffd397,0xbeadf73c,0xbf70c501,0xbf2ac082,0xbf3ebc1b,0xbf65b710,0xbee1fb6a,
0x3f800000,0x0,0x3f7ffec4,0xbbc90f88,0x3f7ffb11,0xbc490e90,0x3f7ff4e6,0xbc96c9b6,0x3fffec43,0xbd490ab0,0x3f7fe129,0xbcfb49ba,0x3f7fd397,0xbd16c32c,0x3f7fc38f,0xbd2fe007,
0x3f800000,0x0,0x3f7ff4e6,0xbc96c9b6,0x3f7fd397,0xbd16c32c,0x3f7f9c18,0xbd621469,0x3fff4e6d,0xbe16a905,0x3f7eea9d,0xbdbc3ac3,0x3f7e70b0,0xbde1bc2e,0x3f7de0b1,0xbe039502,
0x3f800000,0x0,0x3f7fe129,0xbcfb49ba,0x3f7f84ab,0xbd7b2b74,0x3f7eea9d,0xbdbc3ac3,0x3ffe1324,0xbe7ab273,0x3f7cfe73,0xbe1c76de,0x3f7baccd,0xbe3b6ecf,0x3f7a1e84,0xbe5a3997,
0x3f800000,0x0,0x3f7fc38f,0xbd2fe007,0x3f7f0e58,0xbdafb680,0x3f7de0b1,0xbe039502,0x3ffc3b28,0xbeaf10a2,0x3f7a1e84,0xbe5a3997,0x3f778bc5,0xbe827dc0,0x3f748422,0xbe97a117,
0x3f800000,0x0,0x3f7f9c18,0xbd621469,0x3f7e70b0,0xbde1bc2e,0x3f7c7eb0,0xbe28defc,0x3ff9c79d,0xbee05c13,0x3f764d97,0xbe8b9507,0x3f721352,0xbea68f12,0x3f6d1c1d,0xbec1071e,
0x3f800000,0x0,0x3f7f6ac7,0xbd8a200a,0x3f7dabcc,0xbe09cf86,0x3f7ac516,0xbe4dee60,0x3ff6ba07,0xbf088e93,0x3f718f57,0xbea986c4,0x3f6b4b0c,0xbec9b953,0x3f63f473,0xbee900b7,
0x3f800000,0x0,0x3f7f2f9d,0xbda3308c,0x3f7cbfc9,0xbe22abb6,0x3f78b47b,0xbe72b651,0x3ff31447,0xbf209ae5,0x3f6be858,0xbec6d529,0x3f633c5a,0xbeebcbbb,0x3f591e6a,0xbf07a136,
0x3f800000,0x0,0x3f7eea9d,0xbdbc3ac3,0x3f7baccd,0xbe3b6ecf,0x3f764d97,0xbe8b9507,0x3feed89e,0xbf38442a,0x3f655e0b,0xbee363fa,0x3f59f26a,0xbf064b82,0x3f4cae79,0xbf19c200,
0x3f800000,0x0,0x3f7e9bc9,0xbdd53db9,0x3f7a7302,0xbe541501,0x3f73913f,0xbe9d9e78,0x3fea09a7,0xbf4f7bca,0x3f5df6be,0xbeff17b2,0x3f4f7a1f,0xbf15f6d9,0x3f3ebc1b,0xbf2ac082,
0x3f800000,0x0,0x3f7e4323,0xbdee3876,0x3f791298,0xbe6c9a7f,0x3f708066,0xbeaf713a,0x3fe4aa59,0xbf663375,0x3f55b993,0xbf0cead0,0x3f43e200,0xbf24d225,0x3f2f61a5,0xbf3a7ca4,
0x3f800000,0x0,0x3f7de0b1,0xbe039502,0x3f778bc5,0xbe827dc0,0x3f6d1c1d,0xbec1071e,0x3fdebe05,0xbf7c5d27,0x3f4cae79,0xbf19c200,0x3f373a23,0xbf32c8c9,0x3f1ebc12,0xbf48d8b3,
0x3f800000,0x0,0x3f7d7474,0xbe1008b7,0x3f75dec6,0xbe8e9a22,0x3f696591,0xbed25a09,0x3fd84853,0xbf88f59b,0x3f42de29,0xbf26050a,0x3f299415,0xbf3fc767,0x3f0cead0,0xbf55b993,
0x3f800000,0x0,0x3f7cfe73,0xbe1c76de,0x3f740bdd,0xbe9aa086,0x3f655e0b,0xbee363fa,0x3fd14d3d,0xbf93682a,0x3f385216,0xbf31a81d,0x3f1b02c6,0xbf4bbbf8,0x3ef41f07,0xbf6106f2,
0x3f800000,0x0,0x3f7c7eb0,0xbe28defc,0x3f721352,0xbea68f12,0x3f6106f2,0xbef41f07,0x3fc9d112,0xbf9d7fd1,0x3f2d1469,0xbf3ca003,0x3f0b9a6b,0xbf5695e5,0x3ecc9b8b,0xbf6aab7b,
0x3f800000,0x0,0x3f7bf531,0xbe354098,0x3f6ff573,0xbeb263ef,0x3f5c61c7,0xbf0242b1,0x3fc1d870,0xbfa73656,0x3f212ff9,0xbf46e22a,0x3ef6e0cb,0xbf604621,0x3ea395c5,0xbf7294f8,
0x3f800000,0x0,0x3f7b61fc,0xbe419b37,0x3f6db293,0xbebe1d4a,0x3f577026,0xbf0a48ad,0x3fb96842,0xbfb085bb,0x3f14b039,0xbf5064af,0x3ed53641,0xbf68bf3c,0x3e72b651,0xbf78b47b,
0x3f800000,0x0,0x3f7ac516,0xbe4dee60,0x3f6b4b0c,0xbec9b953,0x3f5233c6,0xbf121eb0,0x3fb085bb,0xbfb96842,0x3f07a136,0xbf591e6a,0x3eb263ef,0xbf6ff573,0x3e1c76de,0xbf7cfe73,
0x3f800000,0x0,0x3f7a1e84,0xbe5a3997,0x3f68bf3c,0xbed53641,0x3f4cae79,0xbf19c200,0x3fa73656,0xbfc1d870,0x3ef41f07,0xbf6106f2,0x3e8e9a22,0xbf75dec6,0x3d8a200a,0xbf7f6ac7,
0x3f800000,0x0,0x3f796e4e,0xbe667c66,0x3f660f88,0xbee0924f,0x3f46e22a,0xbf212ff9,0x3f9d7fd1,0xbfc9d112,0x3ed8106b,0xbf6816a8,0x3e541501,0xbf7a7302,0xbc96c9b6,0xbf7ff4e6,
0x3f800000,0x0,0x3f78b47b,0xbe72b651,0x3f633c5a,0xbeebcbbb,0x3f40d0da,0xbf286605,0x3f93682a,0xbfd14d3d,0x3ebb31a0,0xbf6e46be,0x3e09cf86,0xbf7dabcc,0xbdd53db9,0xbf7e9bc9,
0x3f800000,0x0,0x3f77f110,0xbe7ee6e1,0x3f604621,0xbef6e0cb,0x3f3a7ca4,0xbf2f61a5,0x3f88f59b,0xbfd84853,0x3e9d9e78,0xbf73913f,0x3d7b2b74,0xbf7f84ab,0xbe419b37,0xbf7b61fc,
0x3f800000,0x0,0x3f772417,0xbe8586ce,0x3f5d2d53,0xbf00e7e4,0x3f33e7bc,0xbf36206c,0x3f7c5d27,0xbfdebe05,0x3e7ee6e1,0xbf77f110,0xbc490e90,0xbf7ffb11,0xbe8b9507,0xbf764d97,
0x3f800000,0x0,0x3f764d97,0xbe8b9507,0x3f59f26a,0xbf064b82,0x3f2d1469,0xbf3ca003,0x3f663375,0xbfe4aa59,0x3e419b37,0xbf7b61fc,0xbdafb680,0xbf7f0e58,0xbeb554ec,0xbf6f6830,
0x3f800000,0x0,0x3f756d97,0xbe919ddd,0x3f5695e5,0xbf0b9a6b,0x3f26050a,0xbf42de29,0x3f4f7bca,0xbfea09a7,0x3e039502,0xbf7de0b1,0xbe22abb6,0xbf7cbfc9,0xbeddbe79,0xbf66becc,
0x3f800000,0x0,0x3f748422,0xbe97a117,0x3f531849,0xbf10d3cd,0x3f1ebc12,0xbf48d8b3,0x3f38442a,0xbfeed89e,0x3d8a200a,0xbf7f6ac7,0xbe6c9a7f,0xbf791298,0xbf0242b1,0xbf5c61c7,
0x3f800000,0x0,0x3f73913f,0xbe9d9e78,0x3f4f7a1f,0xbf15f6d9,0x3f173c07,0xbf4e8d90,0x3f209ae5,0xbff31447,0x3bc90f88,0xbf7ffec4,0xbe9aa086,0xbf740bdd,0xbf14b039,0xbf5064af,
0x3f800000,0x0,0x3f7294f8,0xbea395c5,0x3f4bbbf8,0xbf1b02c6,0x3f0f8784,0xbf53fac3,0x3f088e93,0xbff6ba07,0xbd621469,0xbf7f9c18,0xbebe1d4a,0xbf6db293,0xbf26050a,0xbf42de29,
0x3f800000,0x0,0x3f718f57,0xbea986c4,0x3f47de65,0xbf1ff6cb,0x3f07a136,0xbf591e6a,0x3ee05c13,0xbff9c79d,0xbdee3876,0xbf7e4323,0xbee0924f,0xbf660f88,0xbf36206c,0xbf33e7bc,
0x3f800000,0x0,0x3f708066,0xbeaf713a,0x3f43e200,0xbf24d225,0x3eff17b2,0xbf5df6be,0x3eaf10a2,0xbffc3b28,0xbe354098,0xbf7bf531,0xbf00e7e4,0xbf5d2d53,0xbf44e3f5,0xbf239da9,
0x3f800000,0x0,0x3f6f6830,0xbeb554ec,0x3f3fc767,0xbf299415,0x3eee9479,0xbf628210,0x3e7ab273,0xbffe1324,0xbe72b651,0xbf78b47b,0xbf10d3cd,0xbf531849,0xbf5233c6,0xbf121eb0,
0x3f800000,0x0,0x3f6e46be,0xbebb31a0,0x3f3b8f3b,0xbf2e3bde,0x3eddbe79,0xbf66becc,0x3e16a905,0xbfff4e6d,0xbe97a117,0xbf748422,0xbf1ff6cb,0xbf47de65,0xbf5df6be,0xbeff17b2,
0x3f800000,0x0,0x3f6d1c1d,0xbec1071e,0x3f373a23,0xbf32c8c9,0x3ecc9b8b,0xbf6aab7b,0x3d490ab0,0xbfffec43,0xbeb554ec,0xbf6f6830,0xbf2e3bde,0xbf3b8f3b,0xbf6816a8,0xbed8106b,
0x3f800000,0x0,0x3f7ffd39,0xbc16cb58,0x3f7ff4e6,0xbc96c9b6,0x3f7fe705,0xbce22a7a,0x3fffd397,0xbd96c32c,0x3f7fba9e,0xbd3c6dd5,0x3f7f9c18,0xbd621469,0x3f7f7808,0xbd83db0a,
0x3f800000,0x0,0x3f7ff0e3,0xbcafea69,0x3f7fc38f,0xbd2fe007,0x3f7f7808,0xbd83db0a,0x3fff0e58,0xbe2fb680,0x3f7e868b,0xbddb7d37,0x3f7de0b1,0xbe039502,0x3f7d1cdd,0xbe195be0,
0x3f800000,0x0,0x3f7fdaaf,0xbd0a342f,0x3f7f6ac7,0xbd8a200a,0x3f7eb069,0xbdcefdb7,0x3ffdabcc,0xbe89cf86,0x3f7c5d3a,0xbe2bf804,0x3f7ac516,0xbe4dee60,0x3f78e3d6,0xbe6fa8b2,
0x3f800000,0x0,0x3f7fba9e,0xbd3c6dd5,0x3f7eea9d,0xbdbc3ac3,0x3f7d906e,0xbe0cec4a,0x3ffbaccd,0xbebb6ecf,0x3f7940c0,0xbe698bba,0x3f764d97,0xbe8b9507,0x3f72d4eb,0xbea21887,
0x3f800000,0x0,0x3f7f90b1,0xbd6ea038,0x3f7e4323,0xbdee3876,0x3f7c187a,0xbe3228d4,0x3ff91298,0xbeec9a7f,0x3f75341d,0xbe931f35,0x3f708066,0xbeaf713a,0x3f6afb8c,0xbecb2aae,
0x3f800000,0x0,0x3f7f5ce9,0xbd9064b4,0x3f7d7474,0xbe1008b7,0x3f7a4910,0xbe57278f,0x3ff5dec6,0xbf0e9a22,0x3f703b37,0xbeb0eacb,0x3f696591,0xbed25a09,0x3f61668a,0xbef2bd43,
0x3f800000,0x0,0x3f7f1f49,0xbda973ba,0x3f7c7eb0,0xbe28defc,0x3f7822d1,0xbe7bdba4,0x3ff21352,0xbf268f12,0x3f6a5ad9,0xbece0bea,0x3f6106f2,0xbef41f07,0x3f5627fe,0xbf0c42c9,
0x3f800000,0x0,0x3f7ed7d4,0xbdc27c39,0x3f7b61fc,0xbe419b37,0x3f75a67b,0xbe901c2c,0x3fedb293,0xbf3e1d4a,0x3f6398ac,0xbeea6681,0x3f577026,0xbf0a48ad,0x3f495521,0xbf1e1e22,
0x3f800000,0x0,0x3f7e868b,0xbddb7d37,0x3f7a1e84,0xbe5a3997,0x3f72d4eb,0xbea21887,0x3fe8bf3c,0xbf553641,0x3f5bfb34,0xbf02ef9f,0x3f4cae79,0xbf19c200,0x3f3b0629,0xbf2ecef7,
0x3f800000,0x0,0x3f7e2b72,0xbdf475c0,0x3f78b47b,0xbe72b651,0x3f6faf1b,0xbeb3dca5,0x3fe33c5a,0xbf6bcbbb,0x3f5389c7,0xbf102dd5,0x3f40d0da,0xbf286605,0x3f2b561b,0xbf3e35c5,
0x3f800000,0x0,0x3f7dc68c,0xbe06b26e,0x3f772417,0xbe8586ce,0x3f6c3624,0xbec5625c,0x3fdd2d53,0xbf80e7e4,0x3f4a4c87,0xbf1ce11f,0x3f33e7bc,0xbf36206c,0x3f1a6293,0xbf4c3578,
0x3f800000,0x0,0x3f7d57de,0xbe1324ca,0x3f756d97,0xbe919ddd,0x3f686b39,0xbed6a399,0x3fd695e5,0xbf8b9a6b,0x3f404c5c,0xbf28fd41,0x3f26050a,0xbf42de29,0x3f084b92,0xbf58b3a1,
0x3f800000,0x0,0x3f7cdf6c,0xbe1f917b,0x3f73913f,0xbe9d9e78,0x3f644fac,0xbee79a5d,0x3fcf7a1f,0xbf95f6d9,0x3f3592e7,0xbf34768f,0x3f173c07,0xbf4e8d90,0x3eea6681,0xbf6398ac,
0x3f800000,0x0,0x3f7c5d3a,0xbe2bf804,0x3f718f57,0xbea986c4,0x3f5fe4e9,0xbef840c8,0x3fc7de65,0xbf9ff6cb,0x3f2a2a80,0xbf3f41fc,0x3f07a136,0xbf591e6a,0x3ec27b55,0xbf6cd007,
0x3f800000,0x0,0x3f7bd14d,0xbe3857ec,0x3f6f6830,0xbeb554ec,0x3f5b2c79,0xbf044889,0x3fbfc767,0xbfa99415,0x3f1e1e22,0xbf495521,0x3eee9479,0xbf628210,0x3e9920fe,0xbf74484b,
0x3f800000,0x0,0x3f7b3bab,0xbe44b0b9,0x3f6d1c1d,0xbec1071e,0x3f5627fe,0xbf0c42c9,0x3fb73a23,0xbfb2c8c9,0x3f11796b,0xbf52a649,0x3ecc9b8b,0xbf6aab7b,0x3e5d4b1a,0xbf79f35e,
0x3f800000,0x0,0x3f7a9c59,0xbe5101f1,0x3f6aab7b,0xbecc9b8b,0x3f50d937,0xbf140c5f,0x3fae3bde,0xbfbb8f3b,0x3f044889,0xbf5b2c79,0x3ea986c4,0xbf718f57,0x3e06b26e,0xbf7dc68c,
0x3f800000,0x0,0x3f79f35e,0xbe5d4b1a,0x3f6816a8,0xbed8106b,0x3f4b41fa,0xbf1ba299,0x3fa4d225,0xbfc3e200,0x3eed3063,0xbf62df7b,0x3e8586ce,0xbf772417,0x3d3c6dd5,0xbf7fba9e,
0x3f800000,0x0,0x3f7940c0,0xbe698bba,0x3f655e0b,0xbee363fa,0x3f456439,0xbf2302d3,0x3f9b02c6,0xbfcbbbf8,0x3ed0eb2a,0xbf69b7e4,0x3e419b37,0xbf7b61fc,0xbd2351cb,0xbf7fcbe2,
0x3f800000,0x0,0x3f788486,0xbe75c35a,0x3f628210,0xbeee9479,0x3f3f41fc,0xbf2a2a80,0x3f90d3cd,0xbfd31849,0x3eb3dca5,0xbf6faf1b,0x3dee3876,0xbf7e4323,0xbe007745,0xbf7dfa38,
0x3f800000,0x0,0x3f77beb7,0xbe80f8c0,0x3f5f8327,0xbef9a02d,0x3f38dd65,0xbf311722,0x3f864b82,0xbfd9f26a,0x3e9620d2,0xbf74bf62,0x3d2fe007,0xbf7fc38f,0xbe57278f,0xbf7a4910,
0x3f800000,0x0,0x3f76ef5b,0xbe870ada,0x3f5c61c7,0xbf0242b1,0x3f3238aa,0xbf37c655,0x3f76e0cb,0xbfe04621,0x3e6fa8b2,0xbf78e3d6,0xbcfb49ba,0xbf7fe129,0xbe9620d2,0xbf74bf62,
0x3f800000,0x0,0x3f76167a,0xbe8d17c0,0x3f591e6a,0xbf07a136,0x3f2b561b,0xbf3e35c5,0x3f60924f,0xbfe60f88,0x3e3228d4,0xbf7c187a,0xbdd53db9,0xbf7e9bc9,0xbebf926f,0xbf6d67a1,
0x3f800000,0x0,0x3f75341d,0xbe931f35,0x3f55b993,0xbf0cead0,0x3f24381a,0xbf446337,0x3f49b953,0xbfeb4b0c,0x3de7fa9a,0xbf7e5a38,0xbe354098,0xbf7bf531,0xbee79a5d,0xbf644fac,
0x3f800000,0x0,0x3f74484b,0xbe9920fe,0x3f5233c6,0xbf121eb0,0x3f1ce11f,0xbf4a4c87,0x3f3263ef,0xbfeff573,0x3d55880e,0xbf7fa6e3,0xbe7ee6e1,0xbf77f110,0xbf06f686,0xbf5988ad,
0x3f800000,0x0,0x3f73530e,0xbe9f1cdf,0x3f4e8d90,0xbf173c07,0x3f1553b7,0xbf4fefa8,0x3f1aa086,0xbff40bdd,0xbc16cb58,0xbf7ffd39,0xbea395c5,0xbf7294f8,0xbf19210f,0xbf4d26fd,
0x3f800000,0x0,0x3f725470,0xbea5129f,0x3f4ac77f,0xbf1c420c,0x3f0d9281,0xbf554aa4,0x3f027dc0,0xbff78bc5,0xbd9064b4,0xbf7f5ce9,0xbec6d529,0xbf6be858,0xbf2a2a80,0xbf3f41fc,
0x3f800000,0x0,0x3f714c7a,0xbeab0201,0x3f46e22a,0xbf212ff9,0x3f05a02c,0xbf5a5ba0,0x3ed41501,0xbffa7302,0xbe06b26e,0xbf7dc68c,0xbee900b7,0xbf63f473,0xbf39f2ac,0xbf2ff3e6,
0x3f800000,0x0,0x3f703b37,0xbeb0eacb,0x3f42de29,0xbf26050a,0x3efafef7,0xbf5f20db,0x3ea2abb6,0xbffcbfc9,0xbe44b0b9,0xbf7b3bab,0xbf04f484,0xbf5ac450,0xbf485bca,0xbf1f599f,
0x3f800000,0x0,0x3f6f20b0,0xbeb6ccc3,0x3f3ebc1b,0xbf2ac082,0x3eea6681,0xbf6398ac,0x3e61bc2e,0xbffe70b0,0xbe80f8c0,0xbf77beb7,0xbf14b039,0xbf5064af,0xbf554aa4,0xbf0d9281,
0x3f800000,0x0,0x3f6dfcf2,0xbebca7af,0x3f3a7ca4,0xbf2f61a5,0x3ed97cb9,0xbf67c187,0x3dfb2b74,0xbfff84ab,0xbe9f1cdf,0xbf73530e,0xbf239da9,0xbf44e3f5,0xbf60a6cf,0xbef58035,
0x3f800000,0x0,0x3f6cd007,0xbec27b55,0x3f36206c,0xbf33e7bc,0x3ec8477c,0xbf6b99fb,0x3cc90e90,0xbffffb11,0xbebca7af,0xbf6dfcf2,0xbf31a81d,0xbf385216,0xbf6a5ad9,0xbece0bea,
0x3f800000,0x0,0x0,0x0,0x0,0x0,0x0,0x0,0x0,0x0,0x0,0x0,0x0,0x0,0x0,0x0,
0x0,0x0,0x0,0x0,0x0,0x0,0x0,0x0,0x0,0x0,0x0,0x0,0x0,0x0,0x0,0x0,
0x0,0x0,0x3e000000,0xbf20dff7,0x3ed0c429,0x0,0x3e000000,0x3e61f78b,0x3e0a8bd4,0x0,0x3e000000,0x3d5413cd,0x3d5df9ad,0x0,0x3e000000,0x3cf043ab,
0x0,0x0,0x3e000000,0x3ccbafaf,0xbd5df9ad,0x0,0x3e000000,0x3cf043ab,0xbe0a8bd4,0x0,0x3e000000,0x3d5413cd,0xbed0c429,0x0,0x3e000000,0x3e61f78b,
0x0,0x0,0x0,0x0,0x3f000000,0x0,0x0,0x3f000000,0x0,0x0,0x0,0x0,0x0,0x0,0x0,0x0,
0x0,0x0,0x0,0x0,0x0,0x0,0x0,0x0,0x0,0x0,0x0,0x0,0x3f000000,0x0,0x0,0xbf000000,
0x0,0x0,0x3e000000,0xbe3f90c7,0xbe8b7e3f,0x0,0x3e000000,0xbeb641af,0x3ea73d75,0x0,0x3e000000,0x3e9a827a,0x3da61ad1,0x0,0x3e000000,0x3dd906bd,
0x0,0x0,0x3e000000,0x3dab0dc1,0xbda61ad1,0x0,0x3e000000,0x3dd906bd,0xbea73d75,0x0,0x3e000000,0x3e9a827a,0x3e8b7e3f,0x0,0x3e000000,0xbeb641af,
0x0,0x0,0x0,0x0,0x0,0x0,0x0,0x0,0x3f000000,0x0,0x0,0x3f000000,0x0,0x0,0x0,0x0,
0x0,0x0,0x0,0x0,0x0,0x0,0x0,0x0,0x3f000000,0x0,0x0,0xbf000000,0x0,0x0,0x0,0x0,
0x0,0x0,0x3e000000,0xbdab0dc1,0xbda61ad1,0x0,0x3e000000,0xbdd906bd,0xbea73d75,0x0,0x3e000000,0xbe9a827a,0x3e8b7e3f,0x0,0x3e000000,0x3eb641af,
0x0,0x0,0x3e000000,0x3e3f90c7,0xbe8b7e3f,0x0,0x3e000000,0x3eb641af,0x3ea73d75,0x0,0x3e000000,0xbe9a827a,0x3da61ad1,0x0,0x3e000000,0xbdd906bd,
0x0,0x0,0x0,0x0,0x0,0x0,0x0,0x0,0x0,0x0,0x0,0x0,0x3f000000,0x0,0x0,0x3f000000,
0x0,0x0,0x0,0x0,0x3f000000,0x0,0x0,0xbf000000,0x0,0x0,0x0,0x0,0x0,0x0,0x0,0x0,
0x0,0x0,0x3e000000,0xbccbafaf,0xbd5df9ad,0x0,0x3e000000,0xbcf043ab,0xbe0a8bd4,0x0,0x3e000000,0xbd5413cd,0xbed0c429,0x0,0x3e000000,0xbe61f78b,
0x0,0x0,0x3e000000,0x3f20dff7,0x3ed0c429,0x0,0x3e000000,0xbe61f78b,0x3e0a8bd4,0x0,0x3e000000,0xbd5413cd,0x3d5df9ad,0x0,0x3e000000,0xbcf043ab,
0x0,0x0,0x0,0x0,0x0,0x0,0x0,0x0,0x0,0x0,0x0,0x0,0x0,0x0,0x0,0x0,
0x3f800000,0x0,0x0,0x0,0x0,0x0,0x0,0x0,0x0,0x0,0x0,0x0,0x0,0x0,0x0,0x0,
};

struct Params {
    const __nv_bfloat16 *wr, *wi, *xb, *lre, *lim, *ldt, *dsk;
    float* out;
};

struct cf { float x, y; };
#define YIELD() asm volatile("pmevent 1;")
#define YS 15
#define YIELD_S1() do { if (YS & 1) YIELD(); } while (0)
#define YIELD_S2() do { if (YS & 2) YIELD(); } while (0)
#define YIELD_S3() do { if (YS & 4) YIELD(); } while (0)
__device__ __forceinline__ uint32_t smem_u32(const void* p) { return (uint32_t)__cvta_generic_to_shared(p); }
__device__ __forceinline__ void mbar_init(uint32_t a, uint32_t c) { asm volatile("mbarrier.init.shared::cta.b64 [%0], %1;" ::"r"(a), "r"(c) : "memory"); }
__device__ __forceinline__ void mbar_expect_tx(uint32_t a, uint32_t b) { asm volatile("mbarrier.arrive.expect_tx.shared::cta.b64 _, [%0], %1;" ::"r"(a), "r"(b) : "memory"); }
__device__ __forceinline__ void mbar_arrive(uint32_t a) { asm volatile("mbarrier.arrive.shared::cta.b64 _, [%0];" ::"r"(a) : "memory"); }
__device__ __forceinline__ uint32_t mbar_try(uint32_t a, uint32_t ph) {
    uint32_t ok;
    asm volatile("{.reg .pred p; mbarrier.try_wait.parity.shared::cta.b64 p, [%1], %2; selp.u32 %0, 1, 0, p;}" : "=r"(ok) : "r"(a), "r"(ph) : "memory");
    return ok;
}
__device__ __forceinline__ void mbar_wait(uint32_t a, uint32_t ph) {
    uint32_t ok, n = 0;
    do { ok = mbar_try(a, ph); } while (!ok && ++n < SPIN_LIMIT);
}
__device__ __forceinline__ void mbar_wait_fast(uint32_t a, uint32_t ph) { if (!mbar_try(a, ph)) mbar_wait(a, ph); }
__device__ __forceinline__ unsigned ld_rlx(const unsigned* p) { unsigned v; asm volatile("ld.relaxed.gpu.global.u32 %0, [%1];" : "=r"(v) : "l"(p) : "memory"); return v; }
__device__ __forceinline__ void wait_cnt(const unsigned* p, unsigned target) {
    unsigned n = 0;
    while ((int)(ld_rlx(p) - target) < 0 && ++n < SPIN_LIMIT) __nanosleep(20);
}
__device__ __forceinline__ void red_hint(unsigned* p) { asm volatile("red.relaxed.gpu.global.add.u32 [%0], 1;" ::"l"(p) : "memory"); }
__device__ __forceinline__ void fence_async() { asm volatile("fence.proxy.async.global;" ::: "memory"); }
__device__ __forceinline__ void fence_async_sm() { asm volatile("fence.proxy.async.shared::cta;" ::: "memory"); }
#define bar_sync(id, n) asm volatile("bar.sync %0, %1;" ::"n"(id), "n"(n) : "memory")
#define bar_arrive(id, n) asm volatile("bar.arrive %0, %1;" ::"n"(id), "n"(n) : "memory")
__device__ __forceinline__ bool elect_one() {
    uint32_t r;
    asm volatile("{.reg .pred p; elect.sync _|p, 0xffffffff; selp.u32 %0, 1, 0, p;}" : "=r"(r));
    return r != 0;
}

__device__ __forceinline__ void tma2d(uint32_t dst, const CUtensorMap* m, int c0, int c1, uint32_t bar) {
    asm volatile("cp.async.bulk.tensor.2d.shared::cluster.global.mbarrier::complete_tx::bytes [%0], [%1, {%3,%4}], [%2];" ::"r"(dst), "l"(m), "r"(bar), "r"(c0), "r"(c1) : "memory");
}
__device__ __forceinline__ void tma2d_mc(uint32_t dst, const CUtensorMap* m, int c0, int c1, uint32_t bar) {
    asm volatile("cp.async.bulk.tensor.2d.shared::cluster.global.mbarrier::complete_tx::bytes.multicast::cluster [%0], [%1, {%3,%4}], [%2], %5;" ::"r"(dst), "l"(m), "r"(bar), "r"(c0), "r"(c1), "h"((uint16_t)3) : "memory");
}
__device__ __forceinline__ void tma4d_mc(uint32_t dst, const CUtensorMap* m, int c0, int c1, int c2, int c3, uint32_t bar) {
    asm volatile("cp.async.bulk.tensor.4d.shared::cluster.global.mbarrier::complete_tx::bytes.multicast::cluster [%0], [%1, {%3,%4,%5,%6}], [%2], %7;" ::"r"(dst), "l"(m), "r"(bar), "r"(c0), "r"(c1), "r"(c2), "r"(c3), "h"((uint16_t)3) : "memory");
}
__device__ __forceinline__ void tma4d(uint32_t dst, const CUtensorMap* m, int c0, int c1, int c2, int c3, uint32_t bar) {
    asm volatile("cp.async.bulk.tensor.4d.shared::cluster.global.mbarrier::complete_tx::bytes [%0], [%1, {%3,%4,%5,%6}], [%2];" ::"r"(dst), "l"(m), "r"(bar), "r"(c0), "r"(c1), "r"(c2), "r"(c3) : "memory");
}
__device__ __forceinline__ void tma2d_st(const CUtensorMap* m, int c0, int c1, uint32_t src) {
    asm volatile("cp.async.bulk.tensor.2d.global.shared::cta.bulk_group [%0, {%2,%3}], [%1];" ::"l"(m), "r"(src), "r"(c0), "r"(c1) : "memory");
}
__device__ __forceinline__ void tma3d_st(const CUtensorMap* m, int c0, int c1, int c2, uint32_t src) {
    asm volatile("cp.async.bulk.tensor.3d.global.shared::cta.bulk_group [%0, {%2,%3,%4}], [%1];" ::"l"(m), "r"(src), "r"(c0), "r"(c1), "r"(c2) : "memory");
}
__device__ __forceinline__ void tma5d(uint32_t dst, const CUtensorMap* m, int c0, int c1, int c2, int c3, int c4, uint32_t bar) {
    asm volatile("cp.async.bulk.tensor.5d.shared::cluster.global.mbarrier::complete_tx::bytes [%0], [%1, {%3,%4,%5,%6,%7}], [%2];" ::"r"(dst), "l"(m), "r"(bar), "r"(c0), "r"(c1), "r"(c2), "r"(c3), "r"(c4) : "memory");
}
__device__ __forceinline__ void tma5d_mc(uint32_t dst, const CUtensorMap* m, int c0, int c1, int c2, int c3, int c4, uint32_t bar) {
    asm volatile("cp.async.bulk.tensor.5d.shared::cluster.global.mbarrier::complete_tx::bytes.multicast::cluster [%0], [%1, {%3,%4,%5,%6,%7}], [%2], %8;" ::"r"(dst), "l"(m), "r"(bar), "r"(c0), "r"(c1), "r"(c2), "r"(c3), "r"(c4), "h"((uint16_t)3) : "memory");
}
__device__ __forceinline__ void bulk_ld(uint32_t dst, const void* src, uint32_t n, uint32_t bar) {
    asm volatile("cp.async.bulk.shared::cluster.global.mbarrier::complete_tx::bytes [%0], [%1], %2, [%3];" ::"r"(dst), "l"(src), "r"(n), "r"(bar) : "memory");
}
__device__ __forceinline__ void bulk_st(void* dst, uint32_t src, uint32_t n) {
    asm volatile("cp.async.bulk.global.shared::cta.bulk_group [%0], [%1], %2;" ::"l"(dst), "r"(src), "r"(n) : "memory");
}
__device__ __forceinline__ void bulk_commit() { asm volatile("cp.async.bulk.commit_group;" ::: "memory"); }
__device__ __forceinline__ void bulk_wait_read() { asm volatile("cp.async.bulk.wait_group.read 0;" ::: "memory"); }
__device__ __forceinline__ void bulk_wait_all() { asm volatile("cp.async.bulk.wait_group 0;" ::: "memory"); }
__device__ __forceinline__ void stsm4(uint32_t a, uint32_t r0, uint32_t r1, uint32_t r2, uint32_t r3) {
    asm volatile("stmatrix.sync.aligned.m8n8.x4.shared.b16 [%0], {%1,%2,%3,%4};" ::"r"(a), "r"(r0), "r"(r1), "r"(r2), "r"(r3) : "memory");
}
__device__ __forceinline__ void sts128(uint32_t a, uint32_t r0, uint32_t r1, uint32_t r2, uint32_t r3) {
    asm volatile("st.shared.v4.b32 [%0], {%1,%2,%3,%4};" ::"r"(a), "r"(r0), "r"(r1), "r"(r2), "r"(r3) : "memory");
}
__device__ __forceinline__ void lds128f(uint32_t a, float& x, float& y, float& z, float& u) { asm volatile("ld.shared.v4.f32 {%0,%1,%2,%3}, [%4];" : "=f"(x), "=f"(y), "=f"(z), "=f"(u) : "r"(a) : "memory"); }
__device__ __forceinline__ cf lds_cf(uint32_t a) { cf v; asm volatile("ld.shared.v2.f32 {%0,%1}, [%2];" : "=f"(v.x), "=f"(v.y) : "r"(a) : "memory"); return v; }
__device__ __forceinline__ void stg128(void* a, uint32_t r0, uint32_t r1, uint32_t r2, uint32_t r3) {
    asm volatile("st.global.v4.b32 [%0], {%1,%2,%3,%4};" ::"l"(a), "r"(r0), "r"(r1), "r"(r2), "r"(r3) : "memory");
}
__device__ __forceinline__ uint32_t opaque32(uint32_t v) { asm volatile("" : "+r"(v)); return v; }
__device__ __forceinline__ const uint8_t* padd(const void* base, uint32_t off) {
    uint64_t r;
    asm("{.reg .u32 l, h; mov.b64 {l, h}, %1; add.cc.u32 l, l, %2; addc.u32 h, h, 0; mov.b64 %0, {l, h};}" : "=l"(r) : "l"(base), "r"(off));
    return (const uint8_t*)r;
}
template <int N, int STRIDE> __device__ __forceinline__ void ldtab(uint32_t (&v)[4 * N], uint32_t off) {
    const uint8_t* a = padd(g_tab, off);
#pragma unroll
    for (int i = 0; i < N; i++)
        asm volatile("ld.global.nc.v4.b32 {%0,%1,%2,%3}, [%4];" : "=r"(v[4 * i]), "=r"(v[4 * i + 1]), "=r"(v[4 * i + 2]), "=r"(v[4 * i + 3]) : "l"(a + i * STRIDE));
}
template <int STRIDE> __device__ __forceinline__ void ldtab_cf(cf (&t)[8], uint32_t off) {
    uint32_t v[16];
    ldtab<4, STRIDE>(v, off);
#pragma unroll
    for (int i = 0; i < 8; i++) t[i] = {__uint_as_float(v[2 * i]), __uint_as_float(v[2 * i + 1])};
}
__device__ __forceinline__ uint32_t lds16(uint32_t a) { uint32_t v; asm volatile("ld.shared.u16 %0, [%1];" : "=r"(v) : "r"(a)); return v; }
__device__ __forceinline__ unsigned get_epoch(uint32_t bars) {
    mbar_wait(bars + B_EP, 0);
    unsigned e;
    asm volatile("ld.shared.u32 %0, [%1];" : "=r"(e) : "r"(bars + B_EPOCH) : "memory");
    return e;
}
__device__ __forceinline__ void sts64(uint32_t a, uint32_t x, uint32_t y) { asm volatile("st.shared.v2.b32 [%0], {%1,%2};" ::"r"(a), "r"(x), "r"(y) : "memory"); }
__device__ __forceinline__ uint32_t pk(float lo, float hi) { uint32_t r; asm("cvt.rn.bf16x2.f32 %0, %1, %2;" : "=r"(r) : "f"(hi), "f"(lo)); return r; }
__device__ __forceinline__ float bf2f(unsigned short v) { return __uint_as_float((uint32_t)v << 16); }

__device__ __forceinline__ uint64_t mkdesc(uint32_t addr, uint32_t lbo, uint32_t sbo, uint32_t swz) {
    return (uint64_t)((addr & 0x3FFFF) >> 4) | ((uint64_t)(lbo >> 4) << 16) | ((uint64_t)(sbo >> 4) << 32) | ((uint64_t)swz << 62);
}
__device__ __forceinline__ uint64_t opaque(uint64_t v) { asm volatile("" : "+l"(v)); return v; }
__device__ __forceinline__ void wg_fence() { asm volatile("wgmma.fence.sync.aligned;" ::: "memory"); }
__device__ __forceinline__ void wg_commit() { asm volatile("wgmma.commit_group.sync.aligned;" ::: "memory"); }
template <int N> __device__ __forceinline__ void wg_wait() { asm volatile("wgmma.wait_group.sync.aligned %0;" ::"n"(N) : "memory"); }
template <int N> __device__ __forceinline__ void pin(float (&d)[N]) {
#pragma unroll
    for (int i = 0; i < N; i++) asm volatile("" : "+f"(d[i])::"memory");
}
template <int N> __device__ __forceinline__ void pinu(uint32_t (&d)[N]) {
#pragma unroll
    for (int i = 0; i < N; i++) asm volatile("" : "+r"(d[i])::"memory");
}

#define R8(d, o) "+f"(d[o]), "+f"(d[o + 1]), "+f"(d[o + 2]), "+f"(d[o + 3]), "+f"(d[o + 4]), "+f"(d[o + 5]), "+f"(d[o + 6]), "+f"(d[o + 7])
#define L8 "%0,%1,%2,%3,%4,%5,%6,%7"
#define L32 L8 ",%8,%9,%10,%11,%12,%13,%14,%15,%16,%17,%18,%19,%20,%21,%22,%23,%24,%25,%26,%27,%28,%29,%30,%31"
#define L56 L32 ",%32,%33,%34,%35,%36,%37,%38,%39,%40,%41,%42,%43,%44,%45,%46,%47,%48,%49,%50,%51,%52,%53,%54,%55"
#define L64 L56 ",%56,%57,%58,%59,%60,%61,%62,%63"

template <int O, int TA, int TB, int N> __device__ __forceinline__ void mma128_ss(float (&d)[N], uint64_t da, uint64_t db, int sc) {
    asm volatile("{.reg .pred p; setp.ne.b32 p, %66, 0;\n"
                 "wgmma.mma_async.sync.aligned.m64n128k16.f32.bf16.bf16 {" L64 "}, %64, %65, p, 1, 1, %67, %68;}"
                 : R8(d, O), R8(d, O + 8), R8(d, O + 16), R8(d, O + 24), R8(d, O + 32), R8(d, O + 40), R8(d, O + 48), R8(d, O + 56)
                 : "l"(da), "l"(db), "r"(sc), "n"(TA), "n"(TB));
}
template <int TB> __device__ __forceinline__ void mma128_rs(float (&d)[64], uint32_t a0, uint32_t a1, uint32_t a2, uint32_t a3, uint64_t db, int sc) {
    asm volatile("{.reg .pred p; setp.ne.b32 p, %69, 0;\n"
                 "wgmma.mma_async.sync.aligned.m64n128k16.f32.bf16.bf16 {" L64 "}, {%64,%65,%66,%67}, %68, p, 1, 1, %70;}"
                 : R8(d, 0), R8(d, 8), R8(d, 16), R8(d, 24), R8(d, 32), R8(d, 40), R8(d, 48), R8(d, 56)
                 : "r"(a0), "r"(a1), "r"(a2), "r"(a3), "l"(db), "r"(sc), "n"(TB));
}
template <int TB> __device__ __forceinline__ void mma64_rs(float (&d)[32], uint32_t a0, uint32_t a1, uint32_t a2, uint32_t a3, uint64_t db, int sc) {
    asm volatile("{.reg .pred p; setp.ne.b32 p, %37, 0;\n"
                 "wgmma.mma_async.sync.aligned.m64n64k16.f32.bf16.bf16 {" L32 "}, {%32,%33,%34,%35}, %36, p, 1, 1, %38;}"
                 : R8(d, 0), R8(d, 8), R8(d, 16), R8(d, 24)
                 : "r"(a0), "r"(a1), "r"(a2), "r"(a3), "l"(db), "r"(sc), "n"(TB));
}
__device__ __forceinline__ void mma112_ss(float (&d)[64], uint64_t da, uint64_t db, int sc) {
    asm volatile("{.reg .pred p; setp.ne.b32 p, %58, 0;\n"
                 "wgmma.mma_async.sync.aligned.m64n112k16.f32.bf16.bf16 {" L56 "}, %56, %57, p, 1, 1, 0, 1;}"
                 : R8(d, 8), R8(d, 16), R8(d, 24), R8(d, 32), R8(d, 40), R8(d, 48), R8(d, 56)
                 : "l"(da), "l"(db), "r"(sc));
}
__device__ __forceinline__ void mma16_rs(float (&d)[64], uint32_t a0, uint32_t a1, uint32_t a2, uint32_t a3, uint64_t db, int sc) {
    asm volatile("{.reg .pred p; setp.ne.b32 p, %13, 0;\n"
                 "wgmma.mma_async.sync.aligned.m64n16k16.f32.bf16.bf16 {" L8 "}, {%8,%9,%10,%11}, %12, p, 1, 1, 1;}"
                 : R8(d, 0)
                 : "r"(a0), "r"(a1), "r"(a2), "r"(a3), "l"(db), "r"(sc));
}

__device__ __forceinline__ cf cmul(cf a, cf b) { return {fmaf(a.x, b.x, -a.y * b.y), fmaf(a.x, b.y, a.y * b.x)}; }
__device__ __forceinline__ cf cmulc(cf a, cf b) { return {fmaf(a.x, b.x, a.y * b.y), fmaf(a.y, b.x, -a.x * b.y)}; }
__device__ __forceinline__ cf cfma(cf a, cf b, cf c) { return {fmaf(a.x, b.x, fmaf(-a.y, b.y, c.x)), fmaf(a.x, b.y, fmaf(a.y, b.x, c.y))}; }
__device__ __forceinline__ cf csq(cf a) { return {fmaf(a.x, a.x, -a.y * a.y), (a.x + a.x) * a.y}; }
__device__ __forceinline__ cf cadd(cf a, cf b) { return {a.x + b.x, a.y + b.y}; }
__device__ __forceinline__ cf csub(cf a, cf b) { return {a.x - b.x, a.y - b.y}; }
__device__ __forceinline__ cf twice_minus(cf a, cf s) { return {fmaf(2.f, a.x, -s.x), fmaf(2.f, a.y, -s.y)}; }
__device__ __forceinline__ cf twid(int m, int M) {
    int r = ((m + M / 2) & (M - 1)) - M / 2;
    float s, c;
    __sincosf((float)r * (-6.283185307179586f / (float)M), &s, &c);
    return {c, s};
}
struct c2 { cf a, b; };
#define YF 1
__device__ __forceinline__ void fin(c2& u) { if (YF) asm volatile("pmevent 1;" : "+f"(u.a.x), "+f"(u.a.y), "+f"(u.b.x), "+f"(u.b.y)); }
__device__ __forceinline__ void fin(c2& u, c2& v) {
    if (YF) asm volatile("pmevent 1;" : "+f"(u.a.x), "+f"(u.a.y), "+f"(u.b.x), "+f"(u.b.y), "+f"(v.a.x), "+f"(v.a.y), "+f"(v.b.x), "+f"(v.b.y));
}
__device__ __forceinline__ c2 mul2(c2 u, cf t) { return {cmul(u.a, t), cmul(u.b, t)}; }
__device__ __forceinline__ c2 mul2(c2 u, c2 t) { return {cmul(u.a, t.a), cmul(u.b, t.b)}; }
__device__ __forceinline__ c2 fma2(c2 u, cf t, c2 c) { return {cfma(u.a, t, c.a), cfma(u.b, t, c.b)}; }
__device__ __forceinline__ c2 fma2(c2 u, c2 t, c2 c) { return {cfma(u.a, t.a, c.a), cfma(u.b, t.b, c.b)}; }
__device__ __forceinline__ c2 twm2(c2 u, c2 s) { return {twice_minus(u.a, s.a), twice_minus(u.b, s.b)}; }
__device__ __forceinline__ void bfly(c2& u, c2& v) { const c2 t = u; u = {cadd(t.a, v.a), cadd(t.b, v.b)}; v = {csub(t.a, v.a), csub(t.b, v.b)}; fin(u, v); }
__device__ __forceinline__ void bfly_mi(c2& u, c2& v) {
    const c2 t = u, z = v;
    u = {{t.a.x + z.a.y, t.a.y - z.a.x}, {t.b.x + z.b.y, t.b.y - z.b.x}};
    v = {{t.a.x - z.a.y, t.a.y + z.a.x}, {t.b.x - z.b.y, t.b.y + z.b.x}};
    fin(u, v);
}
__device__ __forceinline__ void bfly_s(c2& u, c2& v) {
    const float s = 0.70710678118654752f;
    const c2 t = u, z = v;
    u = {{fmaf(s, z.a.x, t.a.x), fmaf(s, z.a.y, t.a.y)}, {fmaf(s, z.b.x, t.b.x), fmaf(s, z.b.y, t.b.y)}};
    v = {{fmaf(-s, z.a.x, t.a.x), fmaf(-s, z.a.y, t.a.y)}, {fmaf(-s, z.b.x, t.b.x), fmaf(-s, z.b.y, t.b.y)}};
    fin(u, v);
}
template <class T> __device__ __forceinline__ void bfly_tw(c2& u0, c2& v0, T t0, c2& u1, c2& v1, T t1) {
    v0 = fma2(v0, t0, u0); fin(v0);
    v1 = fma2(v1, t1, u1); fin(v1);
    const c2 a = twm2(u0, v0), b = twm2(u1, v1);
    u0 = v0; u1 = v1; v0 = a; v1 = b;
    fin(v0, v1);
}
template <bool TW> __device__ __forceinline__ void dft8(c2 (&v)[8], const cf (&tw)[8]) {
    if (TW) {
#pragma unroll
        for (int n = 1; n < 4; n++) { v[n] = mul2(v[n], tw[n]); fin(v[n]); }
        bfly_tw(v[0], v[4], tw[4], v[2], v[6], tw[6]);
        bfly_tw(v[1], v[5], tw[5], v[3], v[7], tw[7]);
    } else {
#pragma unroll
        for (int n = 0; n < 4; n++) bfly(v[n], v[n + 4]);
    }
    bfly(v[0], v[2]); bfly_mi(v[4], v[6]);
    bfly(v[1], v[3]); bfly_mi(v[5], v[7]);
    v[5] = {{v[5].a.x + v[5].a.y, v[5].a.y - v[5].a.x}, {v[5].b.x + v[5].b.y, v[5].b.y - v[5].b.x}};
    v[7] = {{v[7].a.y - v[7].a.x, -v[7].a.x - v[7].a.y}, {v[7].b.y - v[7].b.x, -v[7].b.x - v[7].b.y}};
    fin(v[5], v[7]);
    bfly(v[0], v[1]); bfly_s(v[4], v[5]); bfly_mi(v[2], v[3]); bfly_s(v[6], v[7]);
    const c2 t1 = v[1], t3 = v[3];
    v[1] = v[4]; v[4] = t1; v[3] = v[6]; v[6] = t3;
}

template <int H> __device__ __forceinline__ void prescale(float (&d)[128], cf gam) {
#pragma unroll
    for (int r = 2 * H; r < 64; r += 4) {
        asm volatile("{.reg .f32 s, t, u, v; mul.f32 s, %5, %1; mul.f32 u, %5, %3; mul.f32 t, %4, %1; mul.f32 v, %4, %3; neg.f32 t, t; neg.f32 v, v;\n"
                     "fma.rn.f32 %1, %5, %0, t; fma.rn.f32 %3, %5, %2, v; fma.rn.f32 %0, %4, %0, s; fma.rn.f32 %2, %4, %2, u;}"
                     : "+f"(d[r]), "+f"(d[64 + r]), "+f"(d[r + 1]), "+f"(d[65 + r]) : "f"(gam.x), "f"(gam.y));
        YIELD_S2();
    }
}
template <int H> __device__ __forceinline__ void scan2(float (&d)[128], cf lam, cf st, uint8_t* hptr, uint32_t hm, uint32_t hb, uint32_t& keep) {
    uint32_t hp[32];
#pragma unroll
    for (int u = 0; u < 32; u++) {
        const int r = 4 * (u >> 1) + 2 * H + (u & 1);
        st = cfma(lam, st, {d[r], d[64 + r]});
        d[r] = st.x; d[64 + r] = st.y;
        if ((u & 7) == 7) {
            const int jj = u >> 3;
#pragma unroll
            for (int ri = 0; ri < 2; ri++) {
                const int a = 64 * ri + 16 * jj + 2 * H, o = 8 * jj + 4 * ri;
                hp[o] = pk(d[a], d[a + 4]); hp[o + 1] = pk(d[a + 8], d[a + 12]); hp[o + 2] = pk(d[a + 1], d[a + 5]); hp[o + 3] = pk(d[a + 9], d[a + 13]);
                hp[o + jj] = (hp[o + jj] & hm) | hb;
                stg128(hptr + ri * 16384 + (jj >> 1) * 8192 + (jj & 1) * 512, hp[o], hp[o + 1], hp[o + 2], hp[o + 3]);
            }
            YIELD_S3();
            if (jj > 0) {
#pragma unroll
                for (int i = 8 * jj - 8; i < 8 * jj; i += 2) asm volatile("lop3.b32 %0, %0, %1, %2, 0x80;" : "+r"(keep) : "r"(hp[i]), "r"(hp[i + 1]));
            }
        }
    }
}

__device__ __forceinline__ int pos_of(int n) { return (n & 24) + 4 * (n & 1) + ((n >> 1) & 3); }
__device__ __forceinline__ int unit_of(int role, int u, int& slot) {
    if (role >= 128) {
        const int sp = role - 128, t = sp ? 2 * sp + u : (u == 2 ? 1 : 8 * u);
        slot = t & 7;
        return 32 * t;
    }
    const int g = role & 7, w = (role >> 3) & 3, r = (role >> 5) + 4 * u;
    slot = g ? 32 * g + w + 4 * r : 8 * w + r;
    return (g ? g + 16 * w : ((w & 1) << 4) + ((w & 2) << 2)) + 64 * r;
}
template <int STRIDE> __device__ __forceinline__ bool tags_ok(uint32_t a, uint32_t ep) {
    uint32_t v[4], ok;
#pragma unroll
    for (int i = 0; i < 4; i++) asm volatile("ld.shared.u32 %0, [%1];" : "=r"(v[i]) : "r"(a + i * STRIDE) : "memory");
    asm volatile("{.reg .pred p; .reg .b32 a, b; lop3.b32 a, %1, %2, %5, 0x7e; lop3.b32 b, %3, %4, %5, 0x7e; lop3.b32 a, a, b, 1, 0xa8;\n"
                 "setp.eq.u32 p, a, 0; vote.sync.all.pred p, p, -1; selp.u32 %0, 1, 0, p;}" : "=r"(ok) : "r"(v[0]), "r"(v[1]), "r"(v[2]), "r"(v[3]), "r"(ep));
    return ok;
}
__device__ __forceinline__ void load_w_rows(uint32_t dst, const CUtensorMap* mr, const CUtensorMap* mi, int kap, uint32_t bar) {
    mbar_expect_tx(bar, 8 * WPITCH);
    tma2d(dst, mr, (kap * 1026 >> 4) * 2, 0, bar);
    tma2d(dst + 4 * WPITCH, mi, (kap * 1026 >> 4) * 2, 0, bar);
}
#define SB0 1024
#define RDESC(off) (0x4000004000010000ull + (uint64_t)(SB0 / 16 + (off)))
#define HDESC(off) (0x8000004000200000ull + (uint64_t)(SB0 / 16 + (off)))
template <int O, int TA, int SC, int DA, int DB> __device__ __forceinline__ void mma_g(float (&d)[128]) {
    asm volatile("{.reg .b64 da, db; mov.b64 da, %64; mov.b64 db, %65;\n"
                 "wgmma.mma_async.sync.aligned.m64n128k16.f32.bf16.bf16 {" L64 "}, da, db, %66, 1, 1, %67, 0;}"
                 : R8(d, O), R8(d, O + 8), R8(d, O + 16), R8(d, O + 24), R8(d, O + 32), R8(d, O + 40), R8(d, O + 48), R8(d, O + 56)
                 : "n"(TA ? HDESC(DA) : RDESC(DA)), "n"(RDESC(DB)), "n"(SC), "n"(TA));
}
struct Ring {
    uint32_t full, rel;
    bool sig;
};
__device__ __forceinline__ void ring_release(const Ring& r, int slot) {
    if (r.sig) asm volatile("mbarrier.arrive.shared::cluster.b64 _, [%0];" ::"r"(r.rel + 8 * slot) : "memory");
}
__device__ __forceinline__ void peek(uint32_t a, uint32_t ph) { asm volatile("mbarrier.test_wait.parity.shared::cta.b64 pk, [%0], %1;" ::"r"(a), "r"(ph) : "memory"); }
__device__ __forceinline__ void peek_wait(uint32_t a, uint32_t ph) {
    asm volatile("{.reg .u32 n; @pk bra DONE; mov.u32 n, 0;\n"
                 "LOOP: mbarrier.try_wait.parity.shared::cta.b64 pk, [%0], %1; @pk bra DONE; add.u32 n, n, 1; setp.gt.u32 pk, n, %2; @!pk bra LOOP;\n"
                 "DONE: }" ::"r"(a), "r"(ph), "n"(SPIN_LIMIT) : "memory");
}
#define SL(k) ((k) % NST)
#define PH(k) (((k) / NST) & 1)
#define HANDPOS 5
template <int TA, int SC, int K, int HAND> __device__ __forceinline__ void gemm_step(float (&d)[128], Ring& r, uint32_t f, bool rel, bool hand = false) {
    const int KA = TA ? 128 : 2, a = SL(K) * 2048;
    wg_fence();
    mma_g<0, TA, SC, a, a + 1024>(d);
    mma_g<64, TA, SC, a + 512, a + 1024>(d);
    wg_commit();
    wg_wait<1>();
    if (rel) ring_release(r, SL(K + NST - 1));
    mma_g<0, TA, 1, a + KA, a + 1026>(d);
    peek(r.full + 8 * SL(K + 1), PH(K + 1) ^ f);
    mma_g<64, TA, 1, a + 512 + KA, a + 1026>(d);
    if (HAND && HANDPOS == 4 && hand) bar_arrive(HAND, 256);
    mma_g<0, TA, 1, a + 2 * KA, a + 1028>(d);
    if (HAND && HANDPOS == 5 && hand) bar_arrive(HAND, 256);
    mma_g<64, TA, 1, a + 512 + 2 * KA, a + 1028>(d);
    if (HAND && HANDPOS == 6 && hand) bar_arrive(HAND, 256);
    mma_g<0, TA, 1, a + 3 * KA, a + 1030>(d);
    if (HAND && HANDPOS == 7 && hand) bar_arrive(HAND, 256);
    mma_g<64, TA, 1, a + 512 + 3 * KA, a + 1030>(d);
    wg_commit();
    if (!HAND || !hand) peek_wait(r.full + 8 * SL(K + 1), PH(K + 1) ^ f);
}
template <int K0, class F> __device__ __forceinline__ void gemm1(float (&d)[128], Ring& r, F hook) {
    mbar_wait_fast(r.full + 8 * SL(K0), PH(K0));
    gemm_step<0, 0, K0, 0>(d, r, 0, false);
#pragma unroll 1
    for (int it = 0; it < 3; it++) {
        const uint32_t f = it & 1;
        gemm_step<0, 1, K0 + 1, 0>(d, r, f, true);
        gemm_step<0, 1, K0 + 2, 0>(d, r, f, true);
        gemm_step<0, 1, K0 + 3, 0>(d, r, f, true);
        if (it == 2) hook();
        gemm_step<0, 1, K0 + 4, 0>(d, r, f, true);
        gemm_step<0, 1, K0 + 5, K0 ? 2 : 1>(d, r, f, true, it == 2);
    }
}
template <int O, int K, int J> __device__ __forceinline__ void mma_h(float (&y)[128]) { mma_g<O, 1, 1, SL(K) * 2048 + O * 8 + 128 * J, SL(K) * 2048 + 1024 + 2 * J>(y); }
template <int O, int K> __device__ __forceinline__ void half_step(float (&y)[128]) { mma_h<O, K, 0>(y); mma_h<O, K, 1>(y); mma_h<O, K, 2>(y); mma_h<O, K, 3>(y); }
template <int R, int U> __device__ __forceinline__ void out_piece(float (&y)[128], const uint32_t (&dd)[16], uint32_t x0, uint32_t x1, float* op) {
    const int i = 64 * (R >> 1) + 8 * U + 2 * (R & 1);
    asm("mul.rn.bf16x2 %0, %0, %1;" : "+r"(x0) : "r"(dd[2 * U]));
    asm("mul.rn.bf16x2 %0, %0, %1;" : "+r"(x1) : "r"(dd[2 * U + 1]));
    asm volatile("st.global.v4.f32 [%0], {%1,%2,%3,%4};" ::"l"(op + (32 * (R & 1) + 16 * (R >> 1)) * 2048 + 16 * U),
                 "f"(y[i] + __uint_as_float(x0 << 16)), "f"(y[i + 1] + __uint_as_float(x0 & 0xffff0000u)),
                 "f"(y[i + 4] + __uint_as_float(x1 << 16)), "f"(y[i + 5] + __uint_as_float(x1 & 0xffff0000u)) : "memory");
}
template <int R, int U0> __device__ __forceinline__ void load_x4(uint32_t (&xx)[8], uint32_t xa) {
#pragma unroll
    for (int u = 0; u < 4; u++)
        asm volatile("ld.shared.v2.b32 {%0,%1}, [%2];" : "=r"(xx[2 * u]), "=r"(xx[2 * u + 1]) : "r"((xa ^ (u << 5)) + (3 - R) * 8192 + U0 * 1024) : "memory");
}
__device__ __forceinline__ Ring ring_at(uint32_t sb, int k) {
    Ring r;
    r.full = sb + OFF_BAR + B_FULL;
    asm("mapa.shared::cluster.u32 %0, %1, %2;" : "=r"(r.rel) : "r"(sb + OFF_BAR + B_EMPTY), "r"((threadIdx.x >> 5) & 1));
    r.sig = (threadIdx.x & 95) == 0;
    return r;
}

__global__ void __cluster_dims__(2, 1, 1) __launch_bounds__(512, 1)
fused_kernel(const __grid_constant__ CUtensorMap tmX, const __grid_constant__ CUtensorMap tmBre, const __grid_constant__ CUtensorMap tmBim,
             const __grid_constant__ CUtensorMap tmCre, const __grid_constant__ CUtensorMap tmCim, const __grid_constant__ CUtensorMap tmXd,
             const __grid_constant__ CUtensorMap tmUst, const __grid_constant__ CUtensorMap tmVst,
             const __grid_constant__ CUtensorMap tmWr, const __grid_constant__ CUtensorMap tmWi,
             const __grid_constant__ CUtensorMap tmXA, const Params p) {
    extern __shared__ __align__(1024) uint8_t smraw[];
    const uint32_t sb = smem_u32(smraw);
    asm volatile(".reg .pred pk;");
    if ((sb & 0xFFFFFF) != SB0) return;
    const uint32_t bars = sb + OFF_BAR;
    const int tid = threadIdx.x, rank = blockIdx.x & 1;
    const int wg = __shfl_sync(~0u, tid >> 7, 0), w = __shfl_sync(~0u, tid >> 5, 0) & 3, lane = tid & 31, g = lane >> 2, q = lane & 3;
    int role;
    {
        uint32_t T, n;
        asm("mov.u32 %0, %%smid;" : "=r"(T));
        asm("mov.u32 %0, %%nsmid;" : "=r"(n));
        T = (n == 132 ? T : blockIdx.x) >> 1;
        const uint32_t a = ((T - 32) * 37) >> 8;
        role = 2 * (T < 32 ? 8 * (T & 7) + (T >> 3) : (T < 60 ? 8 * (T - 31 - 7 * a) + 4 + a : (T < 62 ? T + 4 : T - 58))) + rank;
    }
    const bool spare = role >= 128;
    const int tc = ((role >> 3) & 14) + rank, cb = (role >> 1) & 7;
    const int fb = role >> 5, fcb = role & 31, fpos = pos_of(fcb);
    const int nu = spare ? (role == 128 ? 3 : 2) : (fcb ? 2 : 0);

    if (wg == 3) {
        if (elect_one()) {
            if (w == 0) {
                mbar_init(bars + B_FULL, 1); mbar_init(bars + B_FULL + 8, 1);
                fence_async_sm();
                if (!spare) {
                    mbar_expect_tx(bars + B_FULL, 32768);
                    tma5d(sb + 16384, &tmX, 0, 0, 0, 0, tc, bars + B_FULL);
                    tma4d(sb, &tmBre, 0, 0, 0, cb * 4, bars + B_FULL);
                    tma4d(sb + 8192, &tmBim, 0, 0, 0, cb * 4, bars + B_FULL);
                    mbar_expect_tx(bars + B_FULL + 8, 32768);
                    tma5d(sb + 32768 + 16384, &tmX, 64, 0, 0, 0, tc, bars + B_FULL + 8);
                }
            } else if (w == 1) {
#pragma unroll
                for (int o = B_FULL + 16; o < B_HR; o += 8) mbar_init(bars + o, 1);
            } else if (w == 2) {
#pragma unroll
                for (int o = B_HR; o < B_EMPTY; o += 8) mbar_init(bars + o, 1);
            } else {
#pragma unroll
                for (int o = B_EMPTY; o < B_EPOCH; o += 8) mbar_init(bars + o, o < B_LAM ? 2 : (o < B_STGU ? 4 : (o < B_UIN || spare ? 8 : 1)));
            }
            asm volatile("fence.mbarrier_init.release.cluster;" ::: "memory");
            fence_async_sm();
        }
        __syncwarp();
        asm volatile("barrier.cluster.arrive.relaxed.aligned;" ::: "memory");
        asm volatile("setmaxnreg.dec.sync.aligned.u32 24;");
        asm volatile("barrier.cluster.wait.aligned;" ::: "memory");
        if (w == 0) {
            if (!spare && elect_one()) {
                int s = 0, ph = 0;
                STAMP(56);
                mbar_expect_tx(bars + B_XIN, 16384);
                mbar_expect_tx(bars + B_XIN + 8, 16384);
#define XA0 2
#pragma unroll 1
                for (int k = 1; k < NST; k++) {
                    if (k >= 2) mbar_expect_tx(bars + B_FULL + k * 8, 32768);
                    tma4d_mc(sb + k * 32768 + rank * 8192, rank ? &tmBim : &tmBre, k * 64, 0, 0, cb * 4, bars + B_FULL + k * 8);
                    if (k >= 2) tma5d(sb + k * 32768 + 16384, &tmX, k * 64, 0, 0, 0, tc, bars + B_FULL + k * 8);
                }
#pragma unroll 1
                for (int i = 0; i < XA0; i++) tma4d(sb + OFF_F + i * 4096, &tmXA, fcb * 32 + (i >> 2) * 16, 0, (i & 3) * 2, fb, bars + B_XIN + (i >> 2) * 8);
#pragma unroll 1
                for (int k = NST; k < 64; k++) {
                    const uint32_t fbar = bars + B_FULL + s * 8, a = sb + s * 32768;
                    mbar_wait(bars + B_EMPTY + s * 8, ph);
                    if (k < 32) {
                        const int kk = (k & 15) * 64;
                        mbar_expect_tx(fbar, 32768);
                        tma4d_mc(a + rank * 8192, rank ? &tmBim : &tmBre, kk, 0, (k >> 4) * 2, cb * 4, fbar);
                        tma5d(a + 16384, &tmX, kk, 0, 0, 0, tc, fbar);
                    } else {
                        const int kk = k - 32;
                        asm volatile("mbarrier.expect_tx.shared::cta.b64 [%0], 16384;" ::"r"(fbar) : "memory");
                        tma5d_mc(a + 16384 + rank * 8192, (kk & 1) ? &tmCim : &tmCre, (kk >> 1) * 64, 0, 0, 0, cb * 8 + rank * 4, fbar);
                        if ((kk & 7) == 0) { mbar_wait(bars + B_HOWN + kk, 0); STAMPR(45 + (kk >> 3)); }
                        mbar_expect_tx(bars + B_HL + s * 16 + (kk & 1) * 8, 16384);
                        bulk_ld(a, g_H + (size_t)(tc * 32 + kk) * 16384, 16384, bars + B_HL + s * 16 + (kk & 1) * 8);
                    }
                    if (k < NST + 8 - XA0) {
                        const int i = k - NST + XA0;
                        tma4d(sb + OFF_F + i * 4096, &tmXA, fcb * 32 + (i >> 2) * 16, 0, (i & 3) * 2, fb, bars + B_XIN + (i >> 2) * 8);
                    }
                    if (++s == NST) { s = 0; ph ^= 1; }
                }
            }
        } else if (w == 1) {
            const unsigned ep = ld_rlx(g_epoch + role * 8) + 1;
            __syncwarp();
            if (elect_one()) {
                asm volatile("st.relaxed.gpu.global.u32 [%0], %1;" ::"l"(g_epoch + role * 8), "r"(ep) : "memory");
                asm volatile("st.shared.u32 [%0], %1;" ::"r"(bars + B_EPOCH), "r"(ep) : "memory");
                mbar_arrive(bars + B_EP);
            }
            uint32_t lph = 0;
            int slot, kap = unit_of(role, 0, slot);
            if (!spare) mbar_wait(bars + B_STGU, 0);
            STAMP(21);
            if (nu && elect_one()) {
                mbar_expect_tx(bars + B_FG, 8192);
                bulk_ld(sb + OFF_F, (const uint8_t*)g_tab + TAB_FG, 8192, bars + B_FG);
                load_w_rows(sb + OFF_WD, &tmWr, &tmWi, kap, bars + B_WD);
                load_w_rows(sb + OFF_WM, &tmWr, &tmWi, (512 - kap) & 511, bars + B_WM);
            }
            const uint32_t utag = lane * 128 + ((((lane >> 1) & 2) ^ (lane & 3)) << 4) + (lane >> 3) * 4;
            if (!spare) {
#pragma unroll 1
                for (int r = 0; r < 8; r++) {
                    if (elect_one()) {
                        tma2d_st(&tmUst, fb * 2048 + fpos * 64, r * 32, sb + OFF_P + r * 4096);
                        if ((r & 3) == 3) { bulk_commit(); red_hint(g_cnt + (r & 4) * 8); }
                    }
                    if (r < 7) __nanosleep(PACE_U);
                }
                bulk_wait_read();
                STAMP(40);
#pragma unroll 1
                for (int u = 0; u < nu; u++) {
                    wait_cnt(g_cnt + u * 32, 128 * ep);
                    STAMPR(41 + u);
#pragma unroll 1
                    for (int n = 0; n < 4096; n++) {
                        if (elect_one()) { mbar_expect_tx(bars + B_LD, 16384); bulk_ld(sb + OFF_P + u * 16384, g_U + (size_t)(role + u * 128) * 16384, 16384, bars + B_LD); }
                        mbar_wait(bars + B_LD, lph & 1);
                        lph ^= 1;
                        if (tags_ok<4096>(sb + OFF_P + u * 16384 + utag, ep)) break;
                    }
                    if (elect_one()) mbar_arrive(bars + B_UIN + u * 8);
                }
            } else {
                wait_cnt(g_cnt + 32, 128 * ep);
#pragma unroll 1
                for (int n = 0; n < 4096; n++) {
                    if (elect_one()) {
                        mbar_expect_tx(bars + B_LD, 8 * 16384);
#pragma unroll 1
                        for (int r = 0; r < 8; r++) bulk_ld(sb + r * 16384, g_U + (size_t)r * (32 * 16384), 16384, bars + B_LD);
                    }
                    mbar_wait(bars + B_LD, n & 1);
                    bool ok = true;
#pragma unroll 1
                    for (int r = 0; r < 8; r++) ok &= tags_ok<4096>(sb + r * 16384 + utag, ep);
                    if (ok) break;
                }
                if (elect_one()) mbar_arrive(bars + B_RAW);
            }
#pragma unroll 1
            for (int u = 0; u < nu; u++) {
                const int sl = slot;
                const uint32_t src = sb + OFF_P + (kap == 256 ? -32768 : (u == 2 ? -16384 : u * 16384));
                const bool st = kap != 0;
                mbar_wait(bars + B_WFREE, u & 1);
                if (u + 1 < nu) {
                    kap = unit_of(role, u + 1, slot);
                    if (elect_one()) {
                        load_w_rows(sb + OFF_WD, &tmWr, &tmWi, kap, bars + B_WD);
                        load_w_rows(sb + OFF_WM, &tmWr, &tmWi, 512 - kap, bars + B_WM);
                    }
                }
                mbar_wait(bars + B_STG, u & 1);
                STAMPR(23 + u);
                if (st) {
#pragma unroll 1
                    for (int r = 0; r < 4; r++) {
                        if (elect_one()) tma3d_st(&tmVst, sl * 32, (r & 1) * 64, r >> 1, src + r * 4096);
                        if (r < 3) __nanosleep(PACE_V);
                    }
                }
            }
            if (elect_one()) {
                bulk_commit();
                if (nu) red_hint(g_cnt + 64);
                if (!spare) {
                    if (!nu) mbar_arrive(bars + B_FG);
                    mbar_expect_tx(bars + B_FG, 8192);
                    bulk_ld(sb + OFF_F, (const uint8_t*)g_tab + TAB_G + fb * 8192, 8192, bars + B_FG);
                }
            }
            bulk_wait_read();
            STAMP(43);
            if (!spare) {
                wait_cnt(g_cnt + 64, 128 * ep);
                STAMP(44);
                const uint8_t* vsrc = g_V + (size_t)(fb * 32 + fpos) * 32768;
                if (elect_one()) {
                    mbar_expect_tx(bars + B_LD, 16384);
                    bulk_ld(sb + OFF_P + 16384, vsrc + 16384, 16384, bars + B_LD);
                    mbar_expect_tx(bars + B_LD + 8, 16384);
                    bulk_ld(sb + OFF_P, vsrc, 16384, bars + B_LD + 8);
                }
                const uint32_t vtag = sb + OFF_P + lane * 64 + (lane & 8) * 4 + (lane & 2) * 8 + (lane & 4) * 2;
#pragma unroll 1
                for (int h = 0; h < 2; h++) {
#pragma unroll 1
                    for (int n = 0; n < 4096; n++) {
                        mbar_wait(bars + B_LD + h * 8, (lph >> h) & 1);
                        lph ^= 1 << h;
                        if (tags_ok<2048>(vtag + (h ^ 1) * 16384, ep) & tags_ok<2048>(vtag + (h ^ 1) * 16384 + 8192, ep)) break;
                        if (elect_one()) { mbar_expect_tx(bars + B_LD + h * 8, 16384); bulk_ld(sb + OFF_P + (h ^ 1) * 16384, vsrc + (h ^ 1) * 16384, 16384, bars + B_LD + h * 8); }
                    }
                    if (elect_one()) mbar_arrive(bars + B_VIN + (h ^ 1) * 8);
                }
#pragma unroll 1
                for (int r = 0; r < 4; r++) {
                    if (r == 3) mbar_wait(bars + B_P3M, 0); else __nanosleep(PACE_X);
                    if (elect_one()) {
                        if (r == 0) { mbar_expect_tx(bars + B_XD, 24576); mbar_expect_tx(bars + B_XD + 8, 8192); }
                        tma4d(sb + OFF_F + (3 - r) * 8192, &tmXd, 0, tc * 128 + 32 * (r & 1) + 16 * (r >> 1), 0, cb * 2, bars + B_XD + (r == 3) * 8);
                    }
                }
            }
        } else {
            if (w == 2) {
#pragma unroll 1
                for (int u = lane >> 4; u < nu; u += 2) {
                    int slot;
                    const int r0 = unit_of(role, u, slot) + 512 * ((lane >> 1) & 3), r1 = (2048 - r0) & 2047, mir = (lane >> 3) & 1;
                    const unsigned short* wp = (const unsigned short*)((lane & 1) ? p.wi : p.wr);
                    const float a = bf2f(wp[r0 * 513 + mir * 512]), b = bf2f(wp[r1 * 513 + mir * 512]);
                    asm volatile("st.shared.f32 [%0], %1;" ::"r"(sb + OFF_WSP + u * 64 + (lane & 15) * 4), "f"(0.5f * ((lane & 1) ? (mir ? b - a : a - b) : a + b)) : "memory");
                }
                __syncwarp();
                if (lane == 0) mbar_arrive(bars + B_WSP);
            }
            if (!spare) {
                const unsigned ep = get_epoch(bars);
                const uint32_t ca = sb + (q >> 1) * 8192 + (q & 1) * 512 + g * 1040 + q * 4, rb = bars + B_HR - 16 + w * 8;
                uint32_t rph = 0, hph = 0;
                int s = 32 % NST + w - 2, i5 = 0;
#pragma unroll 1
                for (int kk = w - 2; kk < 32; kk += 2) {
                    mbar_wait(bars + B_HL - 16 + s * 16 + w * 8, hph);
#pragma unroll 1
                    for (int n = 0; n < 4096; n++) {
                        if (tags_ok<128>(ca + s * 32768, ep)) break;
                        int k2 = kk;
                        asm volatile("" : "+r"(k2));
                        if (elect_one()) { mbar_expect_tx(rb, 16384); bulk_ld(sb + s * 32768, g_H + (size_t)(tc * 32 + k2) * 16384, 16384, rb); }
                        mbar_wait(rb, rph);
                        rph ^= 1;
                    }
                    if (elect_one()) mbar_arrive(bars + B_FULL + s * 8);
                    s += 2;
                    if (s >= NST) s -= NST;
                    if (++i5 == NST) { i5 = 0; hph ^= 1; }
                }
            }
        }
    } else {
        asm volatile("barrier.cluster.arrive.relaxed.aligned; barrier.cluster.wait.aligned;" ::: "memory");
        STAMP(55);
        asm volatile("setmaxnreg.inc.sync.aligned.u32 152;");
        const int t7 = tid & 127, hf = wg - 1;
        const int mi = lane >> 3, gl = lane & 7;
        if (spare && wg != 2) {
            mbar_wait(bars + B_RAW, 0);
#pragma unroll 1
            for (int it = 0; it < 2 * nu; it++) {
                const int u = it >> 1;
                int slot;
                const float4* pc = (const float4*)((const uint8_t*)g_tab + TAB_PC) + (unit_of(role, u, slot) >> 2);
                const uint32_t off = (tid >> 2) * 128 + (it & 1) * 8192 + q * 16;
                float zr[8], zi[8];
#pragma unroll
                for (int k = 0; k < 8; k++) zr[k] = zi[k] = 0.f;
#pragma unroll 1
                for (int r = 0; r < 8; r++) {
                    const float4 c = __ldg(pc + r);
                    if (c.x == 0.f && c.y == 0.f && c.z == 0.f && c.w == 0.f) continue;
                    float a[4], b[4];
                    lds128f(sb + r * 16384 + off, a[0], a[1], a[2], a[3]);
                    lds128f(sb + r * 16384 + off + 64, b[0], b[1], b[2], b[3]);
#pragma unroll
                    for (int k = 0; k < 8; k++) {
                        const uint32_t ua = __float_as_uint(a[k >> 1]), ub = __float_as_uint(b[k >> 1]);
                        const float x = __uint_as_float((k & 1) ? ua & 0xffff0000u : ua << 16), y = __uint_as_float((k & 1) ? ub & 0xffff0000u : ub << 16);
                        zr[k] = fmaf(c.x, x, fmaf(c.z, y, zr[k]));
                        zi[k] = fmaf(c.y, x, fmaf(c.w, y, zi[k]));
                    }
                }
                const uint32_t dst = sb + OFF_P + (u == 2 ? -16384 : u * 16384) + off;
                sts128(dst, pk(zr[0], zr[1]), pk(zr[2], zr[3]), pk(zr[4], zr[5]), pk(zr[6], zr[7]));
                sts128(dst + 64, pk(zi[0], zi[1]), pk(zi[2], zi[3]), pk(zi[4], zi[5]), pk(zi[6], zi[7]));
                if (it & 1) {
                    fence_async_sm();
                    __syncwarp();
                    if (lane == 0) mbar_arrive(bars + B_UIN + u * 8);
                }
            }
            return;
        }
        if (wg != 0 && !spare) {
            uint32_t f1[16];
            cf tw[8];
            ldtab<4, 2048>(f1, TAB_F1 + t7 * 16);
            ldtab_cf<16>(tw, TAB_TW1 + (t7 >> 2) * 64);
            const uint32_t tmask = (q == (fpos >> 3) && hf == ((fpos >> 2) & 1)) ? ~1u : ~0u, tbit = get_epoch(bars) & ~tmask;
            const uint32_t a0 = sb + OFF_P + (8 * w + gl + 32 * (mi >> 1)) * 128 + (((((mi & 1) << 2) | ((2 * hf) ^ (fpos & 3))) ^ gl) << 4);
            float acc[64];
            const uint64_t dx = opaque(mkdesc(sb + OFF_F + hf * 16384, 2048, 256, 3));
            mbar_wait(bars + B_XIN + hf * 8, 0);
            STAMP(20);
            pinu(f1);
            wg_fence();
#pragma unroll
            for (int j = 0; j < 4; j++)
                mma128_rs<1>(acc, f1[4 * j], f1[4 * j + 1], f1[4 * j + 2], f1[4 * j + 3], dx + j * 32, j);
            wg_commit();
            wg_wait<0>();
            pin(acc);
            pinu(f1);
#pragma unroll
            for (int cl = 0; cl < 2; cl++) {
                c2 v[8];
#pragma unroll
                for (int n = 0; n < 8; n++) {
                    const int i = 4 * (2 * n + cl);
                    v[n] = {{acc[i], acc[i + 2]}, {acc[i + 1], acc[i + 3]}};
                }
                dft8<true>(v, tw);
#pragma unroll
                for (int r = 0; r < 8; r += 2) {
                    uint32_t o0 = pk(v[r].a.x, v[r].b.x), o1 = pk(v[r].a.y, v[r].b.y), o2 = pk(v[r + 1].a.x, v[r + 1].b.x), o3 = pk(v[r + 1].a.y, v[r + 1].b.y);
                    if (cl == 0) { o0 = (o0 & tmask) | tbit; o2 = (o2 & tmask) | tbit; }
                    stsm4((a0 ^ (cl << 4)) + r * 4096, o0, o1, o2, o3);
                }
            }
            fence_async_sm();
            __syncwarp();
            if (lane == 0) mbar_arrive(bars + B_STGU);
        }
        if (wg != 2) {
        if (wg == 0) bar_sync(4, 128); else bar_sync(8, 128);
        asm volatile("setmaxnreg.inc.sync.aligned.u32 168;");
        const int ch0 = wg * 512 + cb * 64;
        if (wg == 1) {
            const int cl = tid & 127, ch = (cl >> 6) * 512 + ((cl >> 3) & 1) * 256 + cb * 32 + ((cl >> 4) & 3) * 8 + (cl & 7);
            const float lr = __bfloat162float(p.lre[ch]), li = __bfloat162float(p.lim[ch]);
            const float dt = __bfloat162float(__float2bfloat16(expf(__bfloat162float(p.ldt[ch]))));
            float sn, cs;
            sincosf(dt * li, &sn, &cs);
            const float ex = expf(dt * lr), br = ex * cs, bi = ex * sn;
            const float inv = 2.0f / (lr * lr + li * li);
            const float cr = ((br - 1.f) * lr + bi * li) * inv, ci = (bi * lr - (br - 1.f) * li) * inv;
            sts128(sb + OFF_LAM + cl * 16, __float_as_uint(br), __float_as_uint(-bi), __float_as_uint(cr), __float_as_uint(-ci));
            mbar_wait(bars + B_EP, 0);
            __syncwarp();
            if (lane == 0) mbar_arrive(bars + B_LAM);
        }
        float d[128];
        if (wg == 1) bar_sync(1, 256);
        STAMPW(0, 10);
        Ring rg = ring_at(sb, role * 66 + wg * 16);
        cf lam[2], M[2];
        unsigned ep;
        const uint32_t lama = sb + OFF_LAM + wg * 1024 + (16 * w + g) * 16;
        auto hook = [&]() {
            mbar_wait_fast(bars + B_LAM, 0);
            lam[0] = lds_cf(lama); lam[1] = lds_cf(lama + 128);
            M[0] = lds_cf(lama + ((lane & 7) - g) * 16); M[1] = lds_cf(lama + ((lane & 7) - g) * 16 + 128);
            asm volatile("ld.shared.u32 %0, [%1];" : "=r"(ep) : "r"(bars + B_EPOCH) : "memory");
        };
        if (wg == 0) gemm1<0>(d, rg, hook); else gemm1<16>(d, rg, hook);
        cf L[2] = {lam[0], lam[1]};
#pragma unroll
        for (int i = 0; i < 7; i++) {
            M[0] = csq(M[0]); M[1] = csq(M[1]);
            if (i < 4) { L[0] = csq(L[0]); L[1] = csq(L[1]); }
            YIELD();
        }
        asm volatile("" : "+f"(M[0].x), "+f"(M[0].y), "+f"(M[1].x), "+f"(M[1].y), "+f"(L[0].x), "+f"(L[0].y), "+f"(L[1].x), "+f"(L[1].y)::"memory");
        wg_wait<0>();
        ring_release(rg, wg ? SL(31) : SL(15));
        pin(d);
        STAMPW(1, 11);
        {
            cf f[2], fb2[2];
#pragma unroll
            for (int i = 0; i < 17; i++) {
#pragma unroll
                for (int h = 0; h < 2; h++) {
                    const int r = 4 * (i >> 1) + 2 * h + (i & 1), r2 = 32 + 4 * ((i - 1) >> 1) + 2 * h + ((i - 1) & 1);
                    if (i < 16) f[h] = i ? cfma(lam[h], f[h], {d[r], -d[64 + r]}) : cf{d[r], -d[64 + r]};
                    if (i > 0) fb2[h] = i > 1 ? cfma(lam[h], fb2[h], {d[r2], -d[64 + r2]}) : cf{d[r2], -d[64 + r2]};
                    if (i && (h || !(YS & 8))) YIELD_S1();
                }
            }
            cf st[2];
            uint4* cbase = g_carry + (ch0 >> 1) + 8 * w;
            const unsigned tag = ep & 15u;
#pragma unroll
            for (int h = 0; h < 2; h++) { f[h] = cfma(L[h], f[h], fb2[h]); L[h] = csq(L[h]); }
            cf s0[2], s1[2], s2[2];
#pragma unroll
            for (int h = 0; h < 2; h++) {
                s0[h] = {__shfl_sync(~0u, f[h].x, 0, 4), __shfl_sync(~0u, f[h].y, 0, 4)};
                s1[h] = {__shfl_sync(~0u, f[h].x, 1, 4), __shfl_sync(~0u, f[h].y, 1, 4)};
                s2[h] = {__shfl_sync(~0u, f[h].x, 2, 4), __shfl_sync(~0u, f[h].y, 2, 4)};
            }
#pragma unroll
            for (int h = 0; h < 2; h++) {
                s1[h] = cfma(L[h], s0[h], s1[h]);
                s2[h] = cfma(L[h], s1[h], s2[h]);
                f[h] = cfma(L[h], s2[h], f[h]);
            }
            if (q == 3)
                asm volatile("{.reg .b64 a, b; mov.b64 a, {%1,%2}; mov.b64 b, {%3,%4}; st.relaxed.gpu.global.v2.b64 [%0], {a, b};}" ::"l"(cbase + g + tc * 512),
                             "r"((__float_as_uint(f[0].x) & ~15u) | tag), "f"(f[0].y), "r"((__float_as_uint(f[1].x) & ~15u) | tag), "f"(f[1].y) : "memory");
            STAMPX(2, 12);
            cf gam[2] = {lds_cf(lama + 8), lds_cf(lama + 136)};
            cf lq[2], Mw[2];
#pragma unroll
            for (int h = 0; h < 2; h++) {
                const cf one = {1.f, 0.f}, L2 = csq(L[h]), M2 = csq(M[h]);
                st[h] = (q & 2) ? ((q & 1) ? s2[h] : s1[h]) : ((q & 1) ? s0[h] : cf{0.f, 0.f});
                YIELD();
                lq[h] = cmul((q & 1) ? L[h] : one, (q & 2) ? L2 : one);
                YIELD();
                Mw[h] = cmul((lane & 8) ? M[h] : one, (lane & 16) ? M2 : one);
                M[h] = csq(M2);
                YIELD();
            }
#pragma unroll
            for (int h = 0; h < 2; h++) { st[h] = cmul(gam[h], st[h]); lq[h] = cmul(gam[h], lq[h]); YIELD(); }
            prescale<0>(d, gam[0]);
            {
                uint32_t fv[4][4];
                unsigned n = 0;
                bool ok;
                do {
                    asm volatile(
                        "{.reg .pred p0, p1, p2, p3; .reg .b64 a0, b0, a1, b1, a2, b2, a3, b3;\n"
                        "setp.ge.s32 p0, %17, 0; setp.ge.s32 p1, %17, 4; setp.ge.s32 p2, %17, 8; setp.ge.s32 p3, %17, 12;\n"
                        "mov.b64 a0, {%18,%18}; mov.b64 b0, a0; mov.b64 a1, a0; mov.b64 b1, a0; mov.b64 a2, a0; mov.b64 b2, a0; mov.b64 a3, a0; mov.b64 b3, a0;\n"
                        "@p0 ld.relaxed.gpu.global.v2.b64 {a0, b0}, [%16];\n"
                        "@p1 ld.relaxed.gpu.global.v2.b64 {a1, b1}, [%16+-32768];\n"
                        "@p2 ld.relaxed.gpu.global.v2.b64 {a2, b2}, [%16+-65536];\n"
                        "@p3 ld.relaxed.gpu.global.v2.b64 {a3, b3}, [%16+-98304];\n"
                        "mov.b64 {%0,%1}, a0; mov.b64 {%2,%3}, b0; mov.b64 {%4,%5}, a1; mov.b64 {%6,%7}, b1;\n"
                        "mov.b64 {%8,%9}, a2; mov.b64 {%10,%11}, b2; mov.b64 {%12,%13}, a3; mov.b64 {%14,%15}, b3;}"
                        : "=r"(fv[0][0]), "=r"(fv[0][1]), "=r"(fv[0][2]), "=r"(fv[0][3]), "=r"(fv[1][0]), "=r"(fv[1][1]), "=r"(fv[1][2]), "=r"(fv[1][3]),
                          "=r"(fv[2][0]), "=r"(fv[2][1]), "=r"(fv[2][2]), "=r"(fv[2][3]), "=r"(fv[3][0]), "=r"(fv[3][1]), "=r"(fv[3][2]), "=r"(fv[3][3])
                        : "l"(cbase + (lane & 7) + (tc - 1 - (lane >> 3)) * 512), "r"(tc - 1 - (lane >> 3)), "r"(tag) : "memory");
                    unsigned bad = 0;
#pragma unroll
                    for (int a = 0; a < 8; a++) bad |= fv[a >> 1][2 * (a & 1)] ^ tag;
                    ok = (bad & 15u) == 0;
                } while (!__all_sync(~0u, ok) && ++n < SPIN_LIMIT);
                STAMPX(53, 54);
                cf P[2];
#pragma unroll
                for (int h = 0; h < 2; h++) P[h] = {__uint_as_float(fv[3][2 * h]), __uint_as_float(fv[3][2 * h + 1])};
#pragma unroll
                for (int a = 2; a >= 0; a--)
#pragma unroll
                    for (int h = 0; h < 2; h++) P[h] = cfma(M[h], P[h], {__uint_as_float(fv[a][2 * h]), __uint_as_float(fv[a][2 * h + 1])});
                lam[0] = lds_cf(lama); lam[1] = lds_cf(lama + 128);
#pragma unroll
                for (int h = 0; h < 2; h++) P[h] = cmul(P[h], Mw[h]);
                float sx[2][4], sy[2][4];
#pragma unroll
                for (int h = 0; h < 2; h++)
#pragma unroll
                    for (int j = 0; j < 4; j++) { sx[h][j] = __shfl_sync(~0u, P[h].x, g + 8 * j); sy[h][j] = __shfl_sync(~0u, P[h].y, g + 8 * j); }
#pragma unroll
                for (int h = 0; h < 2; h++) st[h] = cfma(lq[h], {(sx[h][0] + sx[h][1]) + (sx[h][2] + sx[h][3]), (sy[h][0] + sy[h][1]) + (sy[h][2] + sy[h][3])}, st[h]);
            }
            STAMPX(3, 13);
            uint8_t* hptr = g_H + (size_t)(tc * 32 + wg * 16 + (cb & 6)) * 16384 + ((cb & 1) * 4 + w) * 1024 + g * 64 + ((q ^ (g >> 1)) << 4);
            const bool tg = 4 * (g & 1) + (q ^ (g >> 1)) == (cb & 1) * 4 + w;
            const uint32_t hm = tg ? ~1u : ~0u, hb = ep & ~hm;
            uint32_t keep = sb >> 28;
            scan2<0>(d, lam[0], st[0], hptr, hm, hb, keep);
            __syncwarp();
            if (lane == 0) mbar_arrive(bars + B_HOWN + wg * 16);
            STAMPW(4, 14);
            prescale<1>(d, lds_cf(lama + 136));
            STAMPW(51, 52);
            scan2<1>(d, lam[1], st[1], hptr + 8 * 16384, hm, hb, keep);
            __syncwarp();
            if (lane == 0) mbar_arrive(bars + B_HOWN + wg * 16 + 8 + keep);
            STAMPW(5, 15);
        }
        if (wg == 0) {
            float y[128];
            uint32_t dd[16];
            const uint8_t* dp = (const uint8_t*)(p.dsk + cb * 128) + opaque32(q * 8);
#pragma unroll
            for (int i = 0; i < 8; i++) asm volatile("ld.global.nc.v2.b32 {%0,%1}, [%2];" : "=r"(dd[2 * i]), "=r"(dd[2 * i + 1]) : "l"(dp + 32 * i));
            const int pg = 2 * (g & 3) + (g >> 2);
            float* op = (float*)((uint8_t*)(p.out + (size_t)(tc * 128 + 64 * (w & 1) + 8 * (w >> 1)) * 2048 + 1024 + cb * 128) + opaque32(pg * 8192 + q * 16));
            const uint32_t xa = sb + OFF_F + (16 * (w & 1) + 8 * (w >> 1) + pg) * 128 + (((q >> 1) ^ pg) << 4) + (q & 1) * 8;
            rg = ring_at(sb, role * 66 + 32);
            pinu(dd);
            STAMP(6);
            bar_sync(2, 256);
            STAMP(7);
            mbar_wait_fast(rg.full + SL(32) * 8, PH(32));
            gemm_step<1, 0, 32, 0>(y, rg, 0, false);
#pragma unroll 1
            for (int it = 0;; it++) {
                const uint32_t f = it & 1;
                gemm_step<1, 1, 33, 0>(y, rg, f, true);
                if (SKEW == 5 && it == 5) break;
                gemm_step<1, 1, 34, 0>(y, rg, f, true);
                if (SKEW == 4 && it == 5) break;
                gemm_step<1, 1, 35, 0>(y, rg, f, it != 5);
                if (SKEW == 3 && it == 5) break;
                gemm_step<1, 1, 36, 0>(y, rg, f, it != 5);
                if (SKEW == 2 && it == 5) break;
                gemm_step<1, 1, 37, 0>(y, rg, f, true);
            }
#define HALF0(k) if (64 - SKEW <= k) { wg_fence(); if (k < 63) peek(rg.full + SL(k + 1) * 8, PH(k + 1)); else peek(bars + B_XD, 0); half_step<0, k>(y); \
                  if (k == 59) { wg_commit(); wg_wait<1>(); ring_release(rg, SL(58)); } if (k < 63) peek_wait(rg.full + SL(k + 1) * 8, PH(k + 1)); }
            HALF0(59) HALF0(60) HALF0(61) HALF0(62) HALF0(63)
            wg_commit();
            peek_wait(bars + B_XD, 0);
            uint32_t xa0[8], xa1[8];
            load_x4<0, 0>(xa0, xa);
            wg_fence();
            half_step<64, 64 - SKEW>(y);
            wg_commit();
            wg_wait<1>();
#pragma unroll
            for (int i = 0; i < 64; i++) asm volatile("" : "+f"(y[i])::"memory");
            STAMP(16);
#define MM(n) if (4 + (n) < 4 * SKEW) { wg_fence(); mma_h<64, 65 - SKEW + (n) / 4, (n) % 4>(y); mma_h<64, 65 - SKEW + (n) / 4, (n) % 4 + 1>(y); }
#define OUT4(R, U, X, n) out_piece<R, U>(y, dd, X[0], X[1], op); MM(n) out_piece<R, U + 1>(y, dd, X[2], X[3], op); MM(n + 2) \
                         out_piece<R, U + 2>(y, dd, X[4], X[5], op); MM(n + 4) out_piece<R, U + 3>(y, dd, X[6], X[7], op); MM(n + 6)
            load_x4<0, 4>(xa1, xa);
            OUT4(0, 0, xa0, 0)
            load_x4<1, 0>(xa0, xa);
            OUT4(0, 4, xa1, 8)
            wg_commit();
            load_x4<1, 4>(xa1, xa);
            OUT4(1, 0, xa0, 16)
            load_x4<2, 0>(xa0, xa);
            OUT4(1, 4, xa1, 16)
            STAMP(18);
            wg_wait<0>();
#pragma unroll
            for (int i = 64; i < 128; i++) asm volatile("" : "+f"(y[i])::"memory");
            STAMP(8);
            load_x4<2, 4>(xa1, xa);
            mbar_wait_fast(bars + B_XD + 8, 0);
            OUT4(2, 0, xa0, 16)
            load_x4<3, 0>(xa0, xa);
            OUT4(2, 4, xa1, 16)
            load_x4<3, 4>(xa1, xa);
            OUT4(3, 0, xa0, 16)
            OUT4(3, 4, xa1, 16)
            STAMP(9);
            return;
        }
        bar_sync(8, 128);
        asm volatile("setmaxnreg.dec.sync.aligned.u32 152;");
        } else {
        if (nu) {
            cf T[8];
            ldtab_cf<2048>(T, TAB_T + t7 * 16);
            const uint32_t ep = get_epoch(bars);
            const int ka = pos_of(t7 >> 2);
            mbar_wait(bars + B_WSP, 0);
            mbar_wait(bars + B_FG, 0);
#pragma unroll 1
            for (int u = 0; u < nu; u++) {
                int slot;
                const int kap = unit_of(role, u, slot);
                const uint32_t buf = sb + OFF_P + (u == 2 ? -16384 : u * 16384);
                float acc[64], za[32], zb[32], ya[32], yb[32], vv[64];
                const uint64_t dF = opaque(mkdesc(sb + OFF_F, 16, 1024, 1)), dB = opaque(mkdesc(buf, 4096, 512, 2));
                STAMP3(39);
                mbar_wait(bars + B_UIN + u * 8, 0);
                STAMP3(22);
                wg_fence();
#pragma unroll
                for (int j = 0; j < 4; j++) mma128_ss<0, 0, 1>(acc, dF + j * 2, dB + j * 64, j);
                wg_commit();
                cf be1 = twid(kap + 512 * q, 2048), be2 = csq(be1), be3 = cmul(be1, be2);
                uint32_t wd[4], wm[4];
#pragma unroll
                for (int j = 0; j < 4; j++) {
                    wd[j] = sb + OFF_WD + ((j + q) & 3) * WPITCH + ((2 * kap) & 15) + 2 * ka + 64 * q;
                    wm[j] = sb + OFF_WM + (((kap ? 3 : 4) - j - q) & 3) * WPITCH + ((-2 * kap) & 15) + 1024 - 2 * ka - 64 * q;
                }
                asm volatile("" : "+f"(be1.x), "+f"(be1.y), "+f"(be2.x), "+f"(be2.y), "+f"(be3.x), "+f"(be3.y)::"memory");
                pinu(wd);
                pinu(wm);
                wg_wait<0>();
                pin(acc);
                STAMP3(30);
                uint32_t af[16], ag[16];
#pragma unroll
                for (int b = 0; b < 4; b++) {
                    uint32_t(&o)[16] = b < 2 ? af : ag;
#pragma unroll
                    for (int c = 0; c < 4; c++) {
                        const int i = 4 * (4 * b + c);
                        c2 x = mul2(c2{{acc[i], acc[i + 2]}, {acc[i + 1], acc[i + 3]}}, c2{T[2 * c], T[2 * c + 1]});
                        fin(x);
                        o[4 * c + (b & 1)] = pk(x.a.x, x.a.y);
                        o[4 * c + 2 + (b & 1)] = pk(x.b.x, x.b.y);
                    }
                    if (b & 1) {
                        pinu(o);
                        wg_fence();
#pragma unroll
                        for (int j = 0; j < 4; j++) mma64_rs<0>(b < 2 ? za : zb, o[4 * j], o[4 * j + 1], o[4 * j + 2], o[4 * j + 3], dF + j * 2, j);
                        wg_commit();
                    }
                }
                STAMP3(31);
                mbar_wait(bars + B_WD, u & 1);
                mbar_wait(bars + B_WM, u & 1);
                uint32_t wr[16];
#pragma unroll
                for (int i = 0; i < 16; i++) wr[i] = lds16(wd[i >> 2] + 256 * ((i >> 1) & 1) + (i & 1) * 4 * WPITCH);
                wg_wait<0>();
                pin(za);
                pin(zb);
                pinu(af);
                pinu(ag);
                STAMP3(32);
#pragma unroll
                for (int jb = 0; jb < 4; jb++) {
                    const int i = 8 * jb;
                    c2 s0 = {{za[i], za[i + 4]}, {za[i + 1], za[i + 5]}}, s2 = {{za[i + 2], za[i + 6]}, {za[i + 3], za[i + 7]}};
                    c2 s1 = {{zb[i], zb[i + 4]}, {zb[i + 1], zb[i + 5]}}, s3 = {{zb[i + 2], zb[i + 6]}, {zb[i + 3], zb[i + 7]}};
                    s2 = mul2(s2, be1);
                    fin(s2);
                    bfly_tw(s0, s1, be2, s2, s3, be3);
                    bfly(s0, s2); bfly_mi(s1, s3);
                    c2 W[4];
#pragma unroll
                    for (int j = 0; j < 4; j++) {
                        W[j] = {{__uint_as_float(wr[4 * j] << 16), __uint_as_float(wr[4 * j + 1] << 16)}, {__uint_as_float(wr[4 * j + 2] << 16), __uint_as_float(wr[4 * j + 3] << 16)}};
                        if ((jb & 1) == 0)
                            asm volatile("{.reg .pred p; setp.eq.u32 p, %3, 0; @p ld.shared.v2.f32 {%0,%1}, [%2];}" : "+f"(W[j].a.x), "+f"(W[j].a.y) : "r"(sb + OFF_WSP + u * 64 + jb * 16 + j * 8), "r"(t7));
                    }
                    if (jb < 3) {
#pragma unroll
                        for (int k = 0; k < 16; k++) {
                            const int e = (k >> 1) & 1, pl = (k & 1) * 4 * WPITCH;
                            wr[k] = jb == 0 ? lds16(wd[k >> 2] + 512 + 256 * e + pl) : lds16(wm[k >> 2] - 512 * (jb - 1) - 256 * e + pl);
                        }
                    }
                    if (jb >= 2) {
#pragma unroll
                        for (int j = 0; j < 4; j++) { W[j].a.y = -W[j].a.y; W[j].b.y = -W[j].b.y; }
                    }
                    s0 = mul2(s0, W[0]); fin(s0);
                    s1 = mul2(s1, W[1]); fin(s1);
                    bfly_tw(s0, s2, W[2], s1, s3, W[3]);
                    bfly(s0, s1); bfly_mi(s2, s3);
                    af[4 * jb] = pk(s0.a.x, s0.b.x); af[4 * jb + 1] = pk(s3.a.x, s3.b.x); af[4 * jb + 2] = pk(s0.a.y, s0.b.y); af[4 * jb + 3] = pk(s3.a.y, s3.b.y);
                    ag[4 * jb] = pk(s1.a.x, s1.b.x); ag[4 * jb + 1] = pk(s2.a.x, s2.b.x); ag[4 * jb + 2] = pk(s1.a.y, s1.b.y); ag[4 * jb + 3] = pk(s2.a.y, s2.b.y);
                }
                pinu(af);
                pinu(ag);
                __syncwarp();
                if (lane == 0) mbar_arrive(bars + B_WFREE);
                wg_fence();
#pragma unroll
                for (int j = 0; j < 4; j++) mma64_rs<1>(ya, af[4 * j], af[4 * j + 1], af[4 * j + 2], af[4 * j + 3], dF + j * 128, j);
                wg_commit();
#pragma unroll
                for (int j = 0; j < 4; j++) mma64_rs<1>(yb, ag[4 * j], ag[4 * j + 1], ag[4 * j + 2], ag[4 * j + 3], dF + j * 128, j);
                wg_commit();
                STAMP3(33);
                {
                    const uint32_t a0 = buf + (mi & 1) * 4096 + (16 * w + 8 * (mi >> 1) + gl) * 64 + ((gl >> 1) << 4);
#pragma unroll
                    for (int h = 0; h < 2; h++) {
                        if (h == 0) { wg_wait<1>(); pin(ya); pinu(af); STAMP3(34); } else { wg_wait<0>(); pin(yb); pinu(ag); }
                        const float(&yy)[32] = h ? yb : ya;
#pragma unroll
                        for (int c = 0; c < 4; c++) {
                            const int i = 8 * ((c + 2 * h) & 3), k = 8 * ((c + 2 * h + 1) & 3) + 2;
                            c2 x = {cmulc({yy[i], yy[i + 1]}, T[2 * c]), cmulc({yy[k], yy[k + 1]}, T[2 * c])};
                            fin(x);
                            c2 y = {cmulc({yy[i + 4], yy[i + 5]}, T[2 * c + 1]), cmulc({yy[k + 4], yy[k + 5]}, T[2 * c + 1])};
                            fin(y);
                            stsm4((a0 ^ (c << 4)) + h * 8192, pk(x.a.x, y.a.x), pk(x.b.x, y.b.x), pk(x.a.y, y.a.y), pk(x.b.y, y.b.y));
                        }
                    }
                }
                STAMP3(38);
                fence_async_sm();
                bar_sync(3, 128);
                wg_fence();
#pragma unroll
                for (int j = 0; j < 4; j++) mma128_ss<0, 1, 1>(vv, dF + j * 128, dB + j * 64, j);
                wg_commit();
                STAMP3(35);
                uint32_t va = buf + (8 * w + (g >> 1)) * 64 + (g & 1) * 32 + (((q ^ (slot >> 1)) & 1) << 4) + (q >> 1) * 8, vb = va;
                if (kap == 0) { if (!(g & 1)) va = vb = va - 32768; }
                else if (kap == 256) { if (g & 1) vb -= 49152; else va -= 49152 - 32; }
                const uint32_t tmask = ((g & 1) == ((slot >> 3) & 1) && q == ((slot >> 1) & 2)) ? ~1u : ~0u, tbit = ep & ~tmask;
                wg_wait<0>();
                pin(vv);
                STAMP3(36);
                bar_sync(3, 128);
#pragma unroll
                for (int k = 0; k < 16; k++) {
                    const int b = k >> 2, hh = (k >> 1) & 1, h = k & 1, i = 16 * b + 8 * hh + 2 * h;
                    sts64((b ? vb : va) + hh * 8192 + b * 2048 + h * 256, (pk(vv[i], vv[i + 1]) & tmask) | tbit, pk(vv[i + 4], vv[i + 5]));
                }
                fence_async_sm();
                __syncwarp();
                if (lane == 0) mbar_arrive(bars + B_STG);
            }
        }
        if (spare) return;
        }
        {
            uint32_t sp[8];
            cf tw[8];
            ldtab<2, 2048>(sp, TAB_SP + fb * 4096 + t7 * 16);
            ldtab_cf<16>(tw, TAB_TW3 + fb * 2048 + (t7 >> 2) * 64);
            const uint64_t dF = opaque(mkdesc(sb + OFF_F, 16, 1024, 1)), dB = opaque(mkdesc(sb + OFF_P + hf * 16384, 2048, 256, 3));
            const uint8_t* op = padd(p.out + (1024 + fb) * 2048 + fcb * 32 + hf * 16, (t7 >> 2) * 32768 + (q >> 1) * 16 + (q & 1) * 32);
            float acc[64], out[64];
            mbar_wait(bars + B_VIN + hf * 8, 0);
            mbar_wait(bars + B_FG, 1);
            STAMP(25);
            pinu(sp);
            wg_fence();
#pragma unroll
            for (int j = 0; j < 4; j++) {
                mma112_ss(acc, dF + j * 2, dB + 128 + j * 32, j);
                if (j < 2) mma16_rs(acc, sp[2 * j], 0u, sp[2 * j + 1], 0u, dB + j * 32, j);
                else mma16_rs(acc, 0u, sp[2 * j], 0u, sp[2 * j + 1], dB + j * 32, 1);
            }
            wg_commit();
            wg_wait<0>();
            pin(acc);
            pinu(sp);
            if (lane == 0) mbar_arrive(bars + B_P3M);
#pragma unroll
            for (int cl = 0; cl < 2; cl++) {
                c2 z[8];
#pragma unroll
                for (int n = 0; n < 8; n++) {
                    const int i = 4 * (2 * n + cl);
                    z[n] = {{acc[i], acc[i + 2]}, {acc[i + 1], acc[i + 3]}};
                }
                z[0] = {{z[0].a.x + z[0].a.y, z[0].a.x - z[0].a.y}, {z[0].b.x + z[0].b.y, z[0].b.x - z[0].b.y}};
                z[4] = mul2(z[4], tw[4]);
                fin(z[0], z[4]);
#pragma unroll
                for (int n = 1; n < 4; n++) {
                    const cf iw = n == 1 ? cf{0.38268343236508977f, 0.92387953251128674f}
                                         : (n == 2 ? cf{0.70710678118654752f, 0.70710678118654752f} : cf{0.92387953251128674f, 0.38268343236508977f});
                    c2 y = mul2(z[n], tw[n]);
                    fin(y);
                    const cf t = {tw[8 - n].x, -tw[8 - n].y};
                    c2 E = fma2(c2{{z[8 - n].a.x, -z[8 - n].a.y}, {z[8 - n].b.x, -z[8 - n].b.y}}, t, y);
                    fin(E);
                    z[n] = fma2(twm2(y, E), iw, E);
                    fin(z[n]);
                    z[8 - n] = {{fmaf(2.f, E.a.x, -z[n].a.x), fmaf(-2.f, E.a.y, z[n].a.y)}, {fmaf(2.f, E.b.x, -z[n].b.x), fmaf(-2.f, E.b.y, z[n].b.y)}};
                }
                dft8<false>(z, tw);
#pragma unroll
                for (int m = 0; m < 8; m++) {
                    out[8 * m + 2 * cl] = z[m].a.x; out[8 * m + 2 * cl + 1] = z[m].b.x;
                    out[8 * m + 4 + 2 * cl] = z[m].a.y; out[8 * m + 5 + 2 * cl] = z[m].b.y;
                }
            }
            STAMP(26);
#pragma unroll
            for (int m = 0; m < 16; m++)
                asm volatile("st.global.v4.f32 [%0], {%1,%2,%3,%4};" ::"l"(op + (m - 8) * (1 << 20)), "f"(out[4 * m]), "f"(out[4 * m + 1]), "f"(out[4 * m + 2]), "f"(out[4 * m + 3]) : "memory");
            STAMP(27);
        }
    }
}

typedef CUresult (*EncodeFn)(CUtensorMap*, CUtensorMapDataType, cuuint32_t, void*, const cuuint64_t*, const cuuint64_t*, const cuuint32_t*,
                             const cuuint32_t*, CUtensorMapInterleave, CUtensorMapSwizzle, CUtensorMapL2promotion, CUtensorMapFloatOOBfill);

static CUtensorMap make_map(EncodeFn enc, const void* ptr, int rank, const cuuint64_t* dims, const cuuint64_t* strides, const cuuint32_t* box,
                            CUtensorMapSwizzle swz, CUtensorMapL2promotion promo, CUtensorMapDataType dt = CU_TENSOR_MAP_DATA_TYPE_BFLOAT16) {
    CUtensorMap m;
    const cuuint32_t es[5] = {1, 1, 1, 1, 1};
    enc(&m, dt, rank, const_cast<void*>(ptr), dims, strides, box, es, CU_TENSOR_MAP_INTERLEAVE_NONE, swz, promo,
        CU_TENSOR_MAP_FLOAT_OOB_FILL_NONE);
    return m;
}

extern "C" void kernel_launch(void* const* d_in, const int* in_sizes, int n_in, void* d_out, int out_size) {
    void* fn = nullptr;
    cudaDriverEntryPointQueryResult qr;
    cudaGetDriverEntryPoint("cuTensorMapEncodeTiled", &fn, cudaEnableDefault, &qr);
    EncodeFn enc = (EncodeFn)fn;
    void *pU, *pV;
    cudaGetSymbolAddress(&pU, g_U);
    cudaGetSymbolAddress(&pV, g_V);
    const CUtensorMapL2promotion P256 = CU_TENSOR_MAP_L2_PROMOTION_L2_256B, P0 = CU_TENSOR_MAP_L2_PROMOTION_NONE;

    const cuuint64_t dX[5] = {1024, 2, 4, 16, 16}, sX[4] = {2048, 32 * 2048, 2 * 2048, 128 * 2048};
    const cuuint32_t bX[5] = {64, 2, 4, 16, 1};
    CUtensorMap tmX = make_map(enc, d_in[3], 5, dX, sX, bX, CU_TENSOR_MAP_SWIZZLE_128B, P256);
    const cuuint64_t dXd[4] = {64, 2048, 2, 16}, sXd[3] = {2048, 64 * 2048, 128};
    const cuuint32_t bXd[4] = {64, 16, 2, 2};
    CUtensorMap tmXd = make_map(enc, d_in[3], 4, dXd, sXd, bXd, CU_TENSOR_MAP_SWIZZLE_128B, P256);
    const cuuint64_t dB[4] = {1024, 8, 4, 32}, sB[3] = {2048, 256 * 2048, 8 * 2048};
    const cuuint32_t bB4[4] = {64, 8, 2, 4};
    CUtensorMap tmBre = make_map(enc, d_in[6], 4, dB, sB, bB4, CU_TENSOR_MAP_SWIZZLE_128B, P256);
    CUtensorMap tmBim = make_map(enc, d_in[7], 4, dB, sB, bB4, CU_TENSOR_MAP_SWIZZLE_128B, P256);
    const cuuint64_t dC[5] = {1024, 2, 4, 2, 64}, sC[4] = {2048, 4 * 2048, 2 * 2048, 16 * 2048};
    const cuuint32_t bC[5] = {64, 2, 4, 2, 4};
    CUtensorMap tmCre = make_map(enc, d_in[8], 5, dC, sC, bC, CU_TENSOR_MAP_SWIZZLE_128B, P256);
    CUtensorMap tmCim = make_map(enc, d_in[9], 5, dC, sC, bC, CU_TENSOR_MAP_SWIZZLE_128B, P256);

    const cuuint64_t dU[2] = {8192, 256}, sU[1] = {16384};
    const cuuint32_t bS[2] = {64, 32};
    CUtensorMap tmUst = make_map(enc, pU, 2, dU, sU, bS, CU_TENSOR_MAP_SWIZZLE_128B, P0);
    const cuuint64_t dV[3] = {8192, 128, 2}, sV[2] = {32768, 16384};
    const cuuint32_t bV[3] = {32, 64, 1};
    CUtensorMap tmVst = make_map(enc, pV, 3, dV, sV, bV, CU_TENSOR_MAP_SWIZZLE_NONE, P0);
    const cuuint64_t dA[4] = {1024, 64, 8, 4}, sA[3] = {32 * 2048, 4 * 2048, 2048};
    const cuuint32_t bA[4] = {16, 64, 2, 1};
    CUtensorMap tmXA = make_map(enc, d_in[0], 4, dA, sA, bA, CU_TENSOR_MAP_SWIZZLE_32B, CU_TENSOR_MAP_L2_PROMOTION_L2_128B);
    const cuuint64_t dF[2] = {512 * 1026 / 8, 4}, sF[1] = {512 * 1026};
    const cuuint32_t bF[2] = {WPITCH / 8, 4};
    CUtensorMap tmWr = make_map(enc, d_in[1], 2, dF, sF, bF, CU_TENSOR_MAP_SWIZZLE_NONE, P0, CU_TENSOR_MAP_DATA_TYPE_UINT64);
    CUtensorMap tmWi = make_map(enc, d_in[2], 2, dF, sF, bF, CU_TENSOR_MAP_SWIZZLE_NONE, P0, CU_TENSOR_MAP_DATA_TYPE_UINT64);

    Params p;
    p.wr = (const __nv_bfloat16*)d_in[1];
    p.wi = (const __nv_bfloat16*)d_in[2];
    p.xb = (const __nv_bfloat16*)d_in[3];
    p.lre = (const __nv_bfloat16*)d_in[4];
    p.lim = (const __nv_bfloat16*)d_in[5];
    p.ldt = (const __nv_bfloat16*)d_in[10];
    p.dsk = (const __nv_bfloat16*)d_in[11];
    p.out = (float*)d_out;
    cudaFuncSetAttribute(fused_kernel, cudaFuncAttributeMaxDynamicSharedMemorySize, SMEM_BYTES);
    fused_kernel<<<132, 512, SMEM_BYTES>>>(tmX, tmBre, tmBim, tmCre, tmCim, tmXd, tmUst, tmVst, tmWr, tmWi, tmXA, p);
}
```

```cpp
#include <cuda_runtime.h>
#include <cuda.h>
#include <cuda_bf16.h>
#include <stdint.h>

#define NST 5
#define WPITCH 1056
#define OFF_P (NST * 32768)
#define OFF_F (OFF_P + 32768)
#define OFF_WD (OFF_F + 8192)
#define OFF_WM (OFF_WD + 8 * WPITCH)
#define OFF_BAR (OFF_F + 32768)
#define OFF_LAM (OFF_BAR + 432)
#define OFF_WSP (OFF_LAM + 2048)
#define OFF_PROF (OFF_WSP + 128)
#define SMEM_BYTES OFF_PROF
#define B_FULL 0
#define B_HL 40
#define B_EP 120
#define B_HR 128
#define B_XD 144
#define B_FG 160
#define B_WSP 168
#define B_WD 176
#define B_DONE 184
#define B_LD 192
#define B_RAW 200
#define B_LAM 208
#define B_IN 216
#define B_XIN 248
#define B_EMPTY 256
#define B_STG 320
#define B_WFREE 328
#define B_HOWN 336
#define B_STGU 368
#define B_P3M 384
#define B_EPOCH 416

#define PACE_U 20
#define PACE_V 20
#define XA_PACE 200
#define XA_PACE2 100
#define XA_TAB 0
#define XA_TABP 200
#define PACE_O 0
#define PACE_ON 1
#define XA_PROMO CU_TENSOR_MAP_L2_PROMOTION_L2_128B
#define TAB_T0 500
#define LAM_T0 1000
#define XA_N0 3
#define XA_T0 0
#define PACE_X 200
#define SKEW 4
#define SPIN_LIMIT (1u << 15)

__device__ __align__(1024) uint8_t g_X[8 << 20];
__device__ __align__(1024) uint8_t g_H[8 << 20];
__device__ __align__(1024) uint4 g_carry[16 * 512];
__device__ __align__(128) unsigned g_cnt[128];
__device__ __align__(128) unsigned g_epoch[132 * 8];

#define STAMP(i) do { } while (0)
#define STAMPO(i, o) do { } while (0)
#define STAMPW(a, b) do { } while (0)
#define STAMPX(a, b) do { } while (0)
#define STAMP5(i) do { } while (0)
#define STAMP6(i) do { } while (0)
#define STAMP3(i) do { } while (0)

#define TAB_FG 0
#define TAB_G 8192
#define TAB_F1 40960
#define TAB_T 49152
#define TAB_SP 57344
#define TAB_TW1 73728
#define TAB_TW3 75776
#define TAB_PC 83968
__device__ __align__(1024) const uint32_t g_tab[21248] = {
0x80003d80,0x80003d80,0x80003d80,0x80003d80,0x80003d80,0x80003d80,0x80003d80,0x80003d80,0x80003d80,0x80003d80,0x80003d80,0x80003d80,0x80003d80,0x80003d80,0x80003d80,0x80003d80,
0x80003d80,0x80003d80,0x80003d80,0x80003d80,0x80003d80,0x80003d80,0x80003d80,0x80003d80,0x80003d80,0x80003d80,0x80003d80,0x80003d80,0x80003d80,0x80003d80,0x80003d80,0x80003d80,
0x3d353d35,0x3d35bd35,0xbd35bd35,0xbd353d35,0x80003d80,0x3d800000,0x8000bd80,0xbd800000,0x3d353d35,0x3d35bd35,0xbd35bd35,0xbd353d35,0x80003d80,0x3d800000,0x8000bd80,0xbd800000,
0x3d353d35,0x3d35bd35,0xbd35bd35,0xbd353d35,0x80003d80,0x3d800000,0x8000bd80,0xbd800000,0x3d353d35,0x3d35bd35,0xbd35bd35,0xbd353d35,0x80003d80,0x3d800000,0x8000bd80,0xbd800000,
0x3d800000,0x3d6dbcc4,0x3d35bd35,0x3cc4bd6d,0x3d7bbc48,0x3d55bd0e,0x3d0ebd55,0x3c48bd7b,0x80003d80,0x3cc43d6d,0x3d353d35,0x3d6d3cc4,0x3c483d7b,0x3d0e3d55,0x3d553d0e,0x3d7b3c48,
0xbd800000,0xbd6d3cc4,0xbd353d35,0xbcc43d6d,0xbd7b3c48,0xbd553d0e,0xbd0e3d55,0xbc483d7b,0x8000bd80,0xbcc4bd6d,0xbd35bd35,0xbd6dbcc4,0xbc48bd7b,0xbd0ebd55,0xbd55bd0e,0xbd7bbc48,
0x3d0ebd55,0xbd7bbc48,0x3c483d7b,0x3d55bd0e,0x3d800000,0xbcc4bd6d,0xbd353d35,0x3d6d3cc4,0x3d553d0e,0x3c48bd7b,0xbd7b3c48,0x3d0e3d55,0x80003d80,0x3d6dbcc4,0xbd35bd35,0xbcc43d6d,
0xbd0e3d55,0x3d7b3c48,0xbc48bd7b,0xbd553d0e,0xbd800000,0x3cc43d6d,0x3d35bd35,0xbd6dbcc4,0xbd55bd0e,0xbc483d7b,0x3d7bbc48,0xbd0ebd55,0x8000bd80,0xbd6d3cc4,0x3d353d35,0x3cc4bd6d,
0x80003d80,0x3d353d35,0x3d800000,0x3d35bd35,0x3cc43d6d,0x3d6d3cc4,0x3d6dbcc4,0x3cc4bd6d,0x8000bd80,0xbd35bd35,0xbd800000,0xbd353d35,0xbcc4bd6d,0xbd6dbcc4,0xbd6d3cc4,0xbcc43d6d,
0x80003d80,0x3d353d35,0x3d800000,0x3d35bd35,0x3cc43d6d,0x3d6d3cc4,0x3d6dbcc4,0x3cc4bd6d,0x8000bd80,0xbd35bd35,0xbd800000,0xbd353d35,0xbcc4bd6d,0xbd6dbcc4,0xbd6d3cc4,0xbcc43d6d,
0x3d6d3cc4,0xbcc4bd6d,0xbcc43d6d,0x3d6dbcc4,0x80003d80,0x3d35bd35,0xbd800000,0x3d353d35,0xbd6dbcc4,0x3cc43d6d,0x3cc4bd6d,0xbd6d3cc4,0x8000bd80,0xbd353d35,0x3d800000,0xbd35bd35,
0x3d6d3cc4,0xbcc4bd6d,0xbcc43d6d,0x3d6dbcc4,0x80003d80,0x3d35bd35,0xbd800000,0x3d353d35,0xbd6dbcc4,0x3cc43d6d,0x3cc4bd6d,0xbd6d3cc4,0x8000bd80,0xbd353d35,0x3d800000,0xbd35bd35,
0x3d800000,0x3cc4bd6d,0xbd35bd35,0xbd6d3cc4,0x3d55bd0e,0xbc48bd7b,0xbd7bbc48,0xbd0e3d55,0x8000bd80,0xbd6dbcc4,0xbd353d35,0x3cc43d6d,0xbd0ebd55,0xbd7b3c48,0xbc483d7b,0x3d553d0e,
0xbd800000,0xbcc43d6d,0x3d353d35,0x3d6dbcc4,0xbd553d0e,0x3c483d7b,0x3d7b3c48,0x3d0ebd55,0x80003d80,0x3d6d3cc4,0x3d35bd35,0xbcc4bd6d,0x3d0e3d55,0x3d7bbc48,0x3c48bd7b,0xbd55bd0e,
0x3c48bd7b,0xbd0e3d55,0x3d55bd0e,0xbd7b3c48,0x3d800000,0xbd6dbcc4,0x3d353d35,0xbcc4bd6d,0xbd7bbc48,0x3d553d0e,0xbd0ebd55,0x3c483d7b,0x8000bd80,0xbcc43d6d,0x3d35bd35,0xbd6d3cc4,
0xbc483d7b,0x3d0ebd55,0xbd553d0e,0x3d7bbc48,0xbd800000,0x3d6d3cc4,0xbd35bd35,0x3cc43d6d,0x3d7b3c48,0xbd55bd0e,0x3d0e3d55,0xbc48bd7b,0x80003d80,0x3cc4bd6d,0xbd353d35,0x3d6dbcc4,
0x3d800000,0x3d800000,0x3d800000,0x3d800000,0x3d800000,0x3d800000,0x3d800000,0x3d800000,0x3d800000,0x3d800000,0x3d800000,0x3d800000,0x3d800000,0x3d800000,0x3d800000,0x3d800000,
0x3d800000,0x3d800000,0x3d800000,0x3d800000,0x3d800000,0x3d800000,0x3d800000,0x3d800000,0x3d800000,0x3d800000,0x3d800000,0x3d800000,0x3d800000,0x3d800000,0x3d800000,0x3d800000,
0x3d35bd35,0xbd35bd35,0xbd353d35,0x3d353d35,0x3d800000,0xbd80,0xbd800000,0x3d80,0x3d35bd35,0xbd35bd35,0xbd353d35,0x3d353d35,0x3d800000,0xbd80,0xbd800000,0x3d80,
0x3d35bd35,0xbd35bd35,0xbd353d35,0x3d353d35,0x3d800000,0xbd80,0xbd800000,0x3d80,0x3d35bd35,0xbd35bd35,0xbd353d35,0x3d353d35,0x3d800000,0xbd80,0xbd800000,0x3d80,
0xbd80,0xbcc4bd6d,0xbd35bd35,0xbd6dbcc4,0xbc48bd7b,0xbd0ebd55,0xbd55bd0e,0xbd7bbc48,0x3d800000,0x3d6dbcc4,0x3d35bd35,0x3cc4bd6d,0x3d7bbc48,0x3d55bd0e,0x3d0ebd55,0x3c48bd7b,
0x3d80,0x3cc43d6d,0x3d353d35,0x3d6d3cc4,0x3c483d7b,0x3d0e3d55,0x3d553d0e,0x3d7b3c48,0xbd800000,0xbd6d3cc4,0xbd353d35,0xbcc43d6d,0xbd7b3c48,0xbd553d0e,0xbd0e3d55,0xbc483d7b,
0xbd55bd0e,0xbc483d7b,0x3d7bbc48,0xbd0ebd55,0xbd80,0xbd6d3cc4,0x3d353d35,0x3cc4bd6d,0x3d0ebd55,0xbd7bbc48,0x3c483d7b,0x3d55bd0e,0x3d800000,0xbcc4bd6d,0xbd353d35,0x3d6d3cc4,
0x3d553d0e,0x3c48bd7b,0xbd7b3c48,0x3d0e3d55,0x3d80,0x3d6dbcc4,0xbd35bd35,0xbcc43d6d,0xbd0e3d55,0x3d7b3c48,0xbc48bd7b,0xbd553d0e,0xbd800000,0x3cc43d6d,0x3d35bd35,0xbd6dbcc4,
0x3d800000,0x3d35bd35,0xbd80,0xbd35bd35,0x3d6dbcc4,0x3cc4bd6d,0xbcc4bd6d,0xbd6dbcc4,0xbd800000,0xbd353d35,0x3d80,0x3d353d35,0xbd6d3cc4,0xbcc43d6d,0x3cc43d6d,0x3d6d3cc4,
0x3d800000,0x3d35bd35,0xbd80,0xbd35bd35,0x3d6dbcc4,0x3cc4bd6d,0xbcc4bd6d,0xbd6dbcc4,0xbd800000,0xbd353d35,0x3d80,0x3d353d35,0xbd6d3cc4,0xbcc43d6d,0x3cc43d6d,0x3d6d3cc4,
0x3cc4bd6d,0xbd6d3cc4,0x3d6d3cc4,0xbcc4bd6d,0x3d800000,0xbd35bd35,0x3d80,0x3d35bd35,0xbcc43d6d,0x3d6dbcc4,0xbd6dbcc4,0x3cc43d6d,0xbd800000,0x3d353d35,0xbd80,0xbd353d35,
0x3cc4bd6d,0xbd6d3cc4,0x3d6d3cc4,0xbcc4bd6d,0x3d800000,0xbd35bd35,0x3d80,0x3d35bd35,0xbcc43d6d,0x3d6dbcc4,0xbd6dbcc4,0x3cc43d6d,0xbd800000,0x3d353d35,0xbd80,0xbd353d35,
0xbd80,0xbd6dbcc4,0xbd353d35,0x3cc43d6d,0xbd0ebd55,0xbd7b3c48,0xbc483d7b,0x3d553d0e,0xbd800000,0xbcc43d6d,0x3d353d35,0x3d6dbcc4,0xbd553d0e,0x3c483d7b,0x3d7b3c48,0x3d0ebd55,
0x3d80,0x3d6d3cc4,0x3d35bd35,0xbcc4bd6d,0x3d0e3d55,0x3d7bbc48,0x3c48bd7b,0xbd55bd0e,0x3d800000,0x3cc4bd6d,0xbd35bd35,0xbd6d3cc4,0x3d55bd0e,0xbc48bd7b,0xbd7bbc48,0xbd0e3d55,
0xbd7bbc48,0x3d553d0e,0xbd0ebd55,0x3c483d7b,0xbd80,0xbcc43d6d,0x3d35bd35,0xbd6d3cc4,0xbc483d7b,0x3d0ebd55,0xbd553d0e,0x3d7bbc48,0xbd800000,0x3d6d3cc4,0xbd35bd35,0x3cc43d6d,
0x3d7b3c48,0xbd55bd0e,0x3d0e3d55,0xbc48bd7b,0x3d80,0x3cc4bd6d,0xbd353d35,0x3d6dbcc4,0x3c48bd7b,0xbd0e3d55,0x3d55bd0e,0xbd7b3c48,0x3d800000,0xbd6dbcc4,0x3d353d35,0xbcc4bd6d,
0x80003d80,0x8000bd80,0x80003d80,0x8000bd80,0x3d800000,0xbd800000,0x3d800000,0xbd800000,0x80003d80,0x8000bd80,0x80003d80,0x8000bd80,0x3d800000,0xbd800000,0x3d800000,0xbd800000,
0x80003d80,0x8000bd80,0x80003d80,0x8000bd80,0x3d800000,0xbd800000,0x3d800000,0xbd800000,0x80003d80,0x8000bd80,0x80003d80,0x8000bd80,0x3d800000,0xbd800000,0x3d800000,0xbd800000,
0x3d35bd35,0x3d353d35,0xbd353d35,0xbd35bd35,0x80003d80,0xbd800000,0x8000bd80,0x3d800000,0x3d35bd35,0x3d353d35,0xbd353d35,0xbd35bd35,0x80003d80,0xbd800000,0x8000bd80,0x3d800000,
0x3d35bd35,0x3d353d35,0xbd353d35,0xbd35bd35,0x80003d80,0xbd800000,0x8000bd80,0x3d800000,0x3d35bd35,0x3d353d35,0xbd353d35,0xbd35bd35,0x80003d80,0xbd800000,0x8000bd80,0x3d800000,
0x3d800000,0xbd6d3cc4,0x3d35bd35,0xbcc43d6d,0xbc48bd7b,0x3d0e3d55,0xbd55bd0e,0x3d7b3c48,0x80003d80,0xbcc4bd6d,0x3d353d35,0xbd6dbcc4,0x3d7bbc48,0xbd553d0e,0x3d0ebd55,0xbc483d7b,
0xbd800000,0x3d6dbcc4,0xbd353d35,0x3cc4bd6d,0x3c483d7b,0xbd0ebd55,0x3d553d0e,0xbd7bbc48,0x8000bd80,0x3cc43d6d,0xbd35bd35,0x3d6d3cc4,0xbd7b3c48,0x3d55bd0e,0xbd0e3d55,0x3c48bd7b,
0xbd55bd0e,0x3c48bd7b,0x3d7bbc48,0x3d0e3d55,0x3d800000,0x3cc43d6d,0xbd353d35,0xbd6dbcc4,0x3d0ebd55,0x3d7b3c48,0x3c483d7b,0xbd553d0e,0x80003d80,0xbd6d3cc4,0xbd35bd35,0x3cc4bd6d,
0x3d553d0e,0xbc483d7b,0xbd7b3c48,0xbd0ebd55,0xbd800000,0xbcc4bd6d,0x3d35bd35,0x3d6d3cc4,0xbd0e3d55,0xbd7bbc48,0xbc48bd7b,0x3d55bd0e,0x8000bd80,0x3d6dbcc4,0x3d353d35,0xbcc43d6d,
0x80003d80,0xbd35bd35,0x3d800000,0xbd353d35,0x3d6dbcc4,0xbcc43d6d,0xbcc4bd6d,0x3d6d3cc4,0x8000bd80,0x3d353d35,0xbd800000,0x3d35bd35,0xbd6d3cc4,0x3cc4bd6d,0x3cc43d6d,0xbd6dbcc4,
0x80003d80,0xbd35bd35,0x3d800000,0xbd353d35,0x3d6dbcc4,0xbcc43d6d,0xbcc4bd6d,0x3d6d3cc4,0x8000bd80,0x3d353d35,0xbd800000,0x3d35bd35,0xbd6d3cc4,0x3cc4bd6d,0x3cc43d6d,0xbd6dbcc4,
0x3cc4bd6d,0x3d6dbcc4,0x3d6d3cc4,0x3cc43d6d,0x80003d80,0xbd353d35,0xbd800000,0xbd35bd35,0xbcc43d6d,0xbd6d3cc4,0xbd6dbcc4,0xbcc4bd6d,0x8000bd80,0x3d35bd35,0x3d800000,0x3d353d35,
0x3cc4bd6d,0x3d6dbcc4,0x3d6d3cc4,0x3cc43d6d,0x80003d80,0xbd353d35,0xbd800000,0xbd35bd35,0xbcc43d6d,0xbd6d3cc4,0xbd6dbcc4,0xbcc4bd6d,0x8000bd80,0x3d35bd35,0x3d800000,0x3d353d35,
0x3d800000,0xbcc43d6d,0xbd35bd35,0x3d6dbcc4,0xbd0ebd55,0x3d7bbc48,0xbc483d7b,0xbd55bd0e,0x8000bd80,0x3d6d3cc4,0xbd353d35,0xbcc4bd6d,0xbd553d0e,0xbc48bd7b,0x3d7b3c48,0xbd0e3d55,
0xbd800000,0x3cc4bd6d,0x3d353d35,0xbd6d3cc4,0x3d0e3d55,0xbd7b3c48,0x3c48bd7b,0x3d553d0e,0x80003d80,0xbd6dbcc4,0x3d35bd35,0x3cc43d6d,0x3d55bd0e,0x3c483d7b,0xbd7bbc48,0x3d0ebd55,
0xbd7bbc48,0xbd55bd0e,0xbd0ebd55,0xbc48bd7b,0x3d800000,0x3d6d3cc4,0x3d353d35,0x3cc43d6d,0xbc483d7b,0xbd0e3d55,0xbd553d0e,0xbd7b3c48,0x8000bd80,0x3cc4bd6d,0x3d35bd35,0x3d6dbcc4,
0x3d7b3c48,0x3d553d0e,0x3d0e3d55,0x3c483d7b,0xbd800000,0xbd6dbcc4,0xbd35bd35,0xbcc4bd6d,0x3c48bd7b,0x3d0ebd55,0x3d55bd0e,0x3d7bbc48,0x80003d80,0xbcc43d6d,0xbd353d35,0xbd6d3cc4,
0x3d800000,0xbd800000,0x3d800000,0xbd800000,0xbd80,0x3d80,0xbd80,0x3d80,0x3d800000,0xbd800000,0x3d800000,0xbd800000,0xbd80,0x3d80,0xbd80,0x3d80,
0x3d800000,0xbd800000,0x3d800000,0xbd800000,0xbd80,0x3d80,0xbd80,0x3d80,0x3d800000,0xbd800000,0x3d800000,0xbd800000,0xbd80,0x3d80,0xbd80,0x3d80,
0xbd35bd35,0x3d35bd35,0x3d353d35,0xbd353d35,0x3d800000,0x3d80,0xbd800000,0xbd80,0xbd35bd35,0x3d35bd35,0x3d353d35,0xbd353d35,0x3d800000,0x3d80,0xbd800000,0xbd80,
0xbd35bd35,0x3d35bd35,0x3d353d35,0xbd353d35,0x3d800000,0x3d80,0xbd800000,0xbd80,0xbd35bd35,0x3d35bd35,0x3d353d35,0xbd353d35,0x3d800000,0x3d80,0xbd800000,0xbd80,
0xbd80,0x3cc43d6d,0xbd35bd35,0x3d6d3cc4,0xbd7b3c48,0x3d55bd0e,0xbd0e3d55,0x3c48bd7b,0x3d800000,0xbd6d3cc4,0x3d35bd35,0xbcc43d6d,0xbc48bd7b,0x3d0e3d55,0xbd55bd0e,0x3d7b3c48,
0x3d80,0xbcc4bd6d,0x3d353d35,0xbd6dbcc4,0x3d7bbc48,0xbd553d0e,0x3d0ebd55,0xbc483d7b,0xbd800000,0x3d6dbcc4,0xbd353d35,0x3cc4bd6d,0x3c483d7b,0xbd0ebd55,0x3d553d0e,0xbd7bbc48,
0xbd0e3d55,0xbd7bbc48,0xbc48bd7b,0x3d55bd0e,0xbd80,0x3d6dbcc4,0x3d353d35,0xbcc43d6d,0xbd55bd0e,0x3c48bd7b,0x3d7bbc48,0x3d0e3d55,0x3d800000,0x3cc43d6d,0xbd353d35,0xbd6dbcc4,
0x3d0ebd55,0x3d7b3c48,0x3c483d7b,0xbd553d0e,0x3d80,0xbd6d3cc4,0xbd35bd35,0x3cc4bd6d,0x3d553d0e,0xbc483d7b,0xbd7b3c48,0xbd0ebd55,0xbd800000,0xbcc4bd6d,0x3d35bd35,0x3d6d3cc4,
0x3d800000,0xbd353d35,0xbd80,0x3d353d35,0xbcc4bd6d,0x3d6d3cc4,0xbd6d3cc4,0x3cc4bd6d,0xbd800000,0x3d35bd35,0x3d80,0xbd35bd35,0x3cc43d6d,0xbd6dbcc4,0x3d6dbcc4,0xbcc43d6d,
0x3d800000,0xbd353d35,0xbd80,0x3d353d35,0xbcc4bd6d,0x3d6d3cc4,0xbd6d3cc4,0x3cc4bd6d,0xbd800000,0x3d35bd35,0x3d80,0xbd35bd35,0x3cc43d6d,0xbd6dbcc4,0x3d6dbcc4,0xbcc43d6d,
0xbd6dbcc4,0xbcc4bd6d,0x3cc4bd6d,0x3d6dbcc4,0x3d800000,0x3d353d35,0x3d80,0xbd353d35,0x3d6d3cc4,0x3cc43d6d,0xbcc43d6d,0xbd6d3cc4,0xbd800000,0xbd35bd35,0xbd80,0x3d35bd35,
0xbd6dbcc4,0xbcc4bd6d,0x3cc4bd6d,0x3d6dbcc4,0x3d800000,0x3d353d35,0x3d80,0xbd353d35,0x3d6d3cc4,0x3cc43d6d,0xbcc43d6d,0xbd6d3cc4,0xbd800000,0xbd35bd35,0xbd80,0x3d35bd35,
0xbd80,0x3d6d3cc4,0xbd353d35,0xbcc4bd6d,0xbd553d0e,0xbc48bd7b,0x3d7b3c48,0xbd0e3d55,0xbd800000,0x3cc4bd6d,0x3d353d35,0xbd6d3cc4,0x3d0e3d55,0xbd7b3c48,0x3c48bd7b,0x3d553d0e,
0x3d80,0xbd6dbcc4,0x3d35bd35,0x3cc43d6d,0x3d55bd0e,0x3c483d7b,0xbd7bbc48,0x3d0ebd55,0x3d800000,0xbcc43d6d,0xbd35bd35,0x3d6dbcc4,0xbd0ebd55,0x3d7bbc48,0xbc483d7b,0xbd55bd0e,
0xbc483d7b,0xbd0e3d55,0xbd553d0e,0xbd7b3c48,0xbd80,0x3cc4bd6d,0x3d35bd35,0x3d6dbcc4,0x3d7b3c48,0x3d553d0e,0x3d0e3d55,0x3c483d7b,0xbd800000,0xbd6dbcc4,0xbd35bd35,0xbcc4bd6d,
0x3c48bd7b,0x3d0ebd55,0x3d55bd0e,0x3d7bbc48,0x3d80,0xbcc43d6d,0xbd353d35,0xbd6d3cc4,0xbd7bbc48,0xbd55bd0e,0xbd0ebd55,0xbc48bd7b,0x3d800000,0x3d6d3cc4,0x3d353d35,0x3cc43d6d,
0x80003d80,0x80003d80,0x80003d80,0x80003d80,0x8000bd80,0x8000bd80,0x8000bd80,0x8000bd80,0x80003d80,0x80003d80,0x80003d80,0x80003d80,0x8000bd80,0x8000bd80,0x8000bd80,0x8000bd80,
0x80003d80,0x80003d80,0x80003d80,0x80003d80,0x8000bd80,0x8000bd80,0x8000bd80,0x8000bd80,0x80003d80,0x80003d80,0x80003d80,0x80003d80,0x8000bd80,0x8000bd80,0x8000bd80,0x8000bd80,
0xbd35bd35,0xbd353d35,0x3d353d35,0x3d35bd35,0x80003d80,0x3d800000,0x8000bd80,0xbd800000,0xbd35bd35,0xbd353d35,0x3d353d35,0x3d35bd35,0x80003d80,0x3d800000,0x8000bd80,0xbd800000,
0xbd35bd35,0xbd353d35,0x3d353d35,0x3d35bd35,0x80003d80,0x3d800000,0x8000bd80,0xbd800000,0xbd35bd35,0xbd353d35,0x3d353d35,0x3d35bd35,0x80003d80,0x3d800000,0x8000bd80,0xbd800000,
0x3d800000,0x3d6dbcc4,0x3d35bd35,0x3cc4bd6d,0xbd7b3c48,0xbd553d0e,0xbd0e3d55,0xbc483d7b,0x80003d80,0x3cc43d6d,0x3d353d35,0x3d6d3cc4,0xbc48bd7b,0xbd0ebd55,0xbd55bd0e,0xbd7bbc48,
0xbd800000,0xbd6d3cc4,0xbd353d35,0xbcc43d6d,0x3d7bbc48,0x3d55bd0e,0x3d0ebd55,0x3c48bd7b,0x8000bd80,0xbcc4bd6d,0xbd35bd35,0xbd6dbcc4,0x3c483d7b,0x3d0e3d55,0x3d553d0e,0x3d7b3c48,
0xbd0e3d55,0x3d7b3c48,0xbc48bd7b,0xbd553d0e,0x3d800000,0xbcc4bd6d,0xbd353d35,0x3d6d3cc4,0xbd55bd0e,0xbc483d7b,0x3d7bbc48,0xbd0ebd55,0x80003d80,0x3d6dbcc4,0xbd35bd35,0xbcc43d6d,
0x3d0ebd55,0xbd7bbc48,0x3c483d7b,0x3d55bd0e,0xbd800000,0x3cc43d6d,0x3d35bd35,0xbd6dbcc4,0x3d553d0e,0x3c48bd7b,0xbd7b3c48,0x3d0e3d55,0x8000bd80,0xbd6d3cc4,0x3d353d35,0x3cc4bd6d,
0x80003d80,0x3d353d35,0x3d800000,0x3d35bd35,0xbcc4bd6d,0xbd6dbcc4,0xbd6d3cc4,0xbcc43d6d,0x8000bd80,0xbd35bd35,0xbd800000,0xbd353d35,0x3cc43d6d,0x3d6d3cc4,0x3d6dbcc4,0x3cc4bd6d,
0x80003d80,0x3d353d35,0x3d800000,0x3d35bd35,0xbcc4bd6d,0xbd6dbcc4,0xbd6d3cc4,0xbcc43d6d,0x8000bd80,0xbd35bd35,0xbd800000,0xbd353d35,0x3cc43d6d,0x3d6d3cc4,0x3d6dbcc4,0x3cc4bd6d,
0xbd6dbcc4,0x3cc43d6d,0x3cc4bd6d,0xbd6d3cc4,0x80003d80,0x3d35bd35,0xbd800000,0x3d353d35,0x3d6d3cc4,0xbcc4bd6d,0xbcc43d6d,0x3d6dbcc4,0x8000bd80,0xbd353d35,0x3d800000,0xbd35bd35,
0xbd6dbcc4,0x3cc43d6d,0x3cc4bd6d,0xbd6d3cc4,0x80003d80,0x3d35bd35,0xbd800000,0x3d353d35,0x3d6d3cc4,0xbcc4bd6d,0xbcc43d6d,0x3d6dbcc4,0x8000bd80,0xbd353d35,0x3d800000,0xbd35bd35,
0x3d800000,0x3cc4bd6d,0xbd35bd35,0xbd6d3cc4,0xbd553d0e,0x3c483d7b,0x3d7b3c48,0x3d0ebd55,0x8000bd80,0xbd6dbcc4,0xbd353d35,0x3cc43d6d,0x3d0e3d55,0x3d7bbc48,0x3c48bd7b,0xbd55bd0e,
0xbd800000,0xbcc43d6d,0x3d353d35,0x3d6dbcc4,0x3d55bd0e,0xbc48bd7b,0xbd7bbc48,0xbd0e3d55,0x80003d80,0x3d6d3cc4,0x3d35bd35,0xbcc4bd6d,0xbd0ebd55,0xbd7b3c48,0xbc483d7b,0x3d553d0e,
0xbc483d7b,0x3d0ebd55,0xbd553d0e,0x3d7bbc48,0x3d800000,0xbd6dbcc4,0x3d353d35,0xbcc4bd6d,0x3d7b3c48,0xbd55bd0e,0x3d0e3d55,0xbc48bd7b,0x8000bd80,0xbcc43d6d,0x3d35bd35,0xbd6d3cc4,
0x3c48bd7b,0xbd0e3d55,0x3d55bd0e,0xbd7b3c48,0xbd800000,0x3d6d3cc4,0xbd35bd35,0x3cc43d6d,0xbd7bbc48,0x3d553d0e,0xbd0ebd55,0x3c483d7b,0x80003d80,0x3cc4bd6d,0xbd353d35,0x3d6dbcc4,
0x3d800000,0x3d800000,0x3d800000,0x3d800000,0xbd800000,0xbd800000,0xbd800000,0xbd800000,0x3d800000,0x3d800000,0x3d800000,0x3d800000,0xbd800000,0xbd800000,0xbd800000,0xbd800000,
0x3d800000,0x3d800000,0x3d800000,0x3d800000,0xbd800000,0xbd800000,0xbd800000,0xbd800000,0x3d800000,0x3d800000,0x3d800000,0x3d800000,0xbd800000,0xbd800000,0xbd800000,0xbd800000,
0xbd353d35,0x3d353d35,0x3d35bd35,0xbd35bd35,0x3d800000,0xbd80,0xbd800000,0x3d80,0xbd353d35,0x3d353d35,0x3d35bd35,0xbd35bd35,0x3d800000,0xbd80,0xbd800000,0x3d80,
0xbd353d35,0x3d353d35,0x3d35bd35,0xbd35bd35,0x3d800000,0xbd80,0xbd800000,0x3d80,0xbd353d35,0x3d353d35,0x3d35bd35,0xbd35bd35,0x3d800000,0xbd80,0xbd800000,0x3d80,
0xbd80,0xbcc4bd6d,0xbd35bd35,0xbd6dbcc4,0x3c483d7b,0x3d0e3d55,0x3d553d0e,0x3d7b3c48,0x3d800000,0x3d6dbcc4,0x3d35bd35,0x3cc4bd6d,0xbd7b3c48,0xbd553d0e,0xbd0e3d55,0xbc483d7b,
0x3d80,0x3cc43d6d,0x3d353d35,0x3d6d3cc4,0xbc48bd7b,0xbd0ebd55,0xbd55bd0e,0xbd7bbc48,0xbd800000,0xbd6d3cc4,0xbd353d35,0xbcc43d6d,0x3d7bbc48,0x3d55bd0e,0x3d0ebd55,0x3c48bd7b,
0x3d553d0e,0x3c48bd7b,0xbd7b3c48,0x3d0e3d55,0xbd80,0xbd6d3cc4,0x3d353d35,0x3cc4bd6d,0xbd0e3d55,0x3d7b3c48,0xbc48bd7b,0xbd553d0e,0x3d800000,0xbcc4bd6d,0xbd353d35,0x3d6d3cc4,
0xbd55bd0e,0xbc483d7b,0x3d7bbc48,0xbd0ebd55,0x3d80,0x3d6dbcc4,0xbd35bd35,0xbcc43d6d,0x3d0ebd55,0xbd7bbc48,0x3c483d7b,0x3d55bd0e,0xbd800000,0x3cc43d6d,0x3d35bd35,0xbd6dbcc4,
0x3d800000,0x3d35bd35,0xbd80,0xbd35bd35,0xbd6d3cc4,0xbcc43d6d,0x3cc43d6d,0x3d6d3cc4,0xbd800000,0xbd353d35,0x3d80,0x3d353d35,0x3d6dbcc4,0x3cc4bd6d,0xbcc4bd6d,0xbd6dbcc4,
0x3d800000,0x3d35bd35,0xbd80,0xbd35bd35,0xbd6d3cc4,0xbcc43d6d,0x3cc43d6d,0x3d6d3cc4,0xbd800000,0xbd353d35,0x3d80,0x3d353d35,0x3d6dbcc4,0x3cc4bd6d,0xbcc4bd6d,0xbd6dbcc4,
0xbcc43d6d,0x3d6dbcc4,0xbd6dbcc4,0x3cc43d6d,0x3d800000,0xbd35bd35,0x3d80,0x3d35bd35,0x3cc4bd6d,0xbd6d3cc4,0x3d6d3cc4,0xbcc4bd6d,0xbd800000,0x3d353d35,0xbd80,0xbd353d35,
0xbcc43d6d,0x3d6dbcc4,0xbd6dbcc4,0x3cc43d6d,0x3d800000,0xbd35bd35,0x3d80,0x3d35bd35,0x3cc4bd6d,0xbd6d3cc4,0x3d6d3cc4,0xbcc4bd6d,0xbd800000,0x3d353d35,0xbd80,0xbd353d35,
0xbd80,0xbd6dbcc4,0xbd353d35,0x3cc43d6d,0x3d0e3d55,0x3d7bbc48,0x3c48bd7b,0xbd55bd0e,0xbd800000,0xbcc43d6d,0x3d353d35,0x3d6dbcc4,0x3d55bd0e,0xbc48bd7b,0xbd7bbc48,0xbd0e3d55,
0x3d80,0x3d6d3cc4,0x3d35bd35,0xbcc4bd6d,0xbd0ebd55,0xbd7b3c48,0xbc483d7b,0x3d553d0e,0x3d800000,0x3cc4bd6d,0xbd35bd35,0xbd6d3cc4,0xbd553d0e,0x3c483d7b,0x3d7b3c48,0x3d0ebd55,
0x3d7b3c48,0xbd55bd0e,0x3d0e3d55,0xbc48bd7b,0xbd80,0xbcc43d6d,0x3d35bd35,0xbd6d3cc4,0x3c48bd7b,0xbd0e3d55,0x3d55bd0e,0xbd7b3c48,0xbd800000,0x3d6d3cc4,0xbd35bd35,0x3cc43d6d,
0xbd7bbc48,0x3d553d0e,0xbd0ebd55,0x3c483d7b,0x3d80,0x3cc4bd6d,0xbd353d35,0x3d6dbcc4,0xbc483d7b,0x3d0ebd55,0xbd553d0e,0x3d7bbc48,0x3d800000,0xbd6dbcc4,0x3d353d35,0xbcc4bd6d,
0x80003d80,0x8000bd80,0x80003d80,0x8000bd80,0xbd800000,0x3d800000,0xbd800000,0x3d800000,0x80003d80,0x8000bd80,0x80003d80,0x8000bd80,0xbd800000,0x3d800000,0xbd800000,0x3d800000,
0x80003d80,0x8000bd80,0x80003d80,0x8000bd80,0xbd800000,0x3d800000,0xbd800000,0x3d800000,0x80003d80,0x8000bd80,0x80003d80,0x8000bd80,0xbd800000,0x3d800000,0xbd800000,0x3d800000,
0xbd353d35,0xbd35bd35,0x3d35bd35,0x3d353d35,0x80003d80,0xbd800000,0x8000bd80,0x3d800000,0xbd353d35,0xbd35bd35,0x3d35bd35,0x3d353d35,0x80003d80,0xbd800000,0x8000bd80,0x3d800000,
0xbd353d35,0xbd35bd35,0x3d35bd35,0x3d353d35,0x80003d80,0xbd800000,0x8000bd80,0x3d800000,0xbd353d35,0xbd35bd35,0x3d35bd35,0x3d353d35,0x80003d80,0xbd800000,0x8000bd80,0x3d800000,
0x3d800000,0xbd6d3cc4,0x3d35bd35,0xbcc43d6d,0x3c483d7b,0xbd0ebd55,0x3d553d0e,0xbd7bbc48,0x80003d80,0xbcc4bd6d,0x3d353d35,0xbd6dbcc4,0xbd7b3c48,0x3d55bd0e,0xbd0e3d55,0x3c48bd7b,
0xbd800000,0x3d6dbcc4,0xbd353d35,0x3cc4bd6d,0xbc48bd7b,0x3d0e3d55,0xbd55bd0e,0x3d7b3c48,0x8000bd80,0x3cc43d6d,0xbd35bd35,0x3d6d3cc4,0x3d7bbc48,0xbd553d0e,0x3d0ebd55,0xbc483d7b,
0x3d553d0e,0xbc483d7b,0xbd7b3c48,0xbd0ebd55,0x3d800000,0x3cc43d6d,0xbd353d35,0xbd6dbcc4,0xbd0e3d55,0xbd7bbc48,0xbc48bd7b,0x3d55bd0e,0x80003d80,0xbd6d3cc4,0xbd35bd35,0x3cc4bd6d,
0xbd55bd0e,0x3c48bd7b,0x3d7bbc48,0x3d0e3d55,0xbd800000,0xbcc4bd6d,0x3d35bd35,0x3d6d3cc4,0x3d0ebd55,0x3d7b3c48,0x3c483d7b,0xbd553d0e,0x8000bd80,0x3d6dbcc4,0x3d353d35,0xbcc43d6d,
0x80003d80,0xbd35bd35,0x3d800000,0xbd353d35,0xbd6d3cc4,0x3cc4bd6d,0x3cc43d6d,0xbd6dbcc4,0x8000bd80,0x3d353d35,0xbd800000,0x3d35bd35,0x3d6dbcc4,0xbcc43d6d,0xbcc4bd6d,0x3d6d3cc4,
0x80003d80,0xbd35bd35,0x3d800000,0xbd353d35,0xbd6d3cc4,0x3cc4bd6d,0x3cc43d6d,0xbd6dbcc4,0x8000bd80,0x3d353d35,0xbd800000,0x3d35bd35,0x3d6dbcc4,0xbcc43d6d,0xbcc4bd6d,0x3d6d3cc4,
0xbcc43d6d,0xbd6d3cc4,0xbd6dbcc4,0xbcc4bd6d,0x80003d80,0xbd353d35,0xbd800000,0xbd35bd35,0x3cc4bd6d,0x3d6dbcc4,0x3d6d3cc4,0x3cc43d6d,0x8000bd80,0x3d35bd35,0x3d800000,0x3d353d35,
0xbcc43d6d,0xbd6d3cc4,0xbd6dbcc4,0xbcc4bd6d,0x80003d80,0xbd353d35,0xbd800000,0xbd35bd35,0x3cc4bd6d,0x3d6dbcc4,0x3d6d3cc4,0x3cc43d6d,0x8000bd80,0x3d35bd35,0x3d800000,0x3d353d35,
0x3d800000,0xbcc43d6d,0xbd35bd35,0x3d6dbcc4,0x3d0e3d55,0xbd7b3c48,0x3c48bd7b,0x3d553d0e,0x8000bd80,0x3d6d3cc4,0xbd353d35,0xbcc4bd6d,0x3d55bd0e,0x3c483d7b,0xbd7bbc48,0x3d0ebd55,
0xbd800000,0x3cc4bd6d,0x3d353d35,0xbd6d3cc4,0xbd0ebd55,0x3d7bbc48,0xbc483d7b,0xbd55bd0e,0x80003d80,0xbd6dbcc4,0x3d35bd35,0x3cc43d6d,0xbd553d0e,0xbc48bd7b,0x3d7b3c48,0xbd0e3d55,
0x3d7b3c48,0x3d553d0e,0x3d0e3d55,0x3c483d7b,0x3d800000,0x3d6d3cc4,0x3d353d35,0x3cc43d6d,0x3c48bd7b,0x3d0ebd55,0x3d55bd0e,0x3d7bbc48,0x8000bd80,0x3cc4bd6d,0x3d35bd35,0x3d6dbcc4,
0xbd7bbc48,0xbd55bd0e,0xbd0ebd55,0xbc48bd7b,0xbd800000,0xbd6dbcc4,0xbd35bd35,0xbcc4bd6d,0xbc483d7b,0xbd0e3d55,0xbd553d0e,0xbd7b3c48,0x80003d80,0xbcc43d6d,0xbd353d35,0xbd6d3cc4,
0x3d800000,0xbd800000,0x3d800000,0xbd800000,0x3d80,0xbd80,0x3d80,0xbd80,0x3d800000,0xbd800000,0x3d800000,0xbd800000,0x3d80,0xbd80,0x3d80,0xbd80,
0x3d800000,0xbd800000,0x3d800000,0xbd800000,0x3d80,0xbd80,0x3d80,0xbd80,0x3d800000,0xbd800000,0x3d800000,0xbd800000,0x3d80,0xbd80,0x3d80,0xbd80,
0x3d353d35,0xbd353d35,0xbd35bd35,0x3d35bd35,0x3d800000,0x3d80,0xbd800000,0xbd80,0x3d353d35,0xbd353d35,0xbd35bd35,0x3d35bd35,0x3d800000,0x3d80,0xbd800000,0xbd80,
0x3d353d35,0xbd353d35,0xbd35bd35,0x3d35bd35,0x3d800000,0x3d80,0xbd800000,0xbd80,0x3d353d35,0xbd353d35,0xbd35bd35,0x3d35bd35,0x3d800000,0x3d80,0xbd800000,0xbd80,
0xbd80,0x3cc43d6d,0xbd35bd35,0x3d6d3cc4,0x3d7bbc48,0xbd553d0e,0x3d0ebd55,0xbc483d7b,0x3d800000,0xbd6d3cc4,0x3d35bd35,0xbcc43d6d,0x3c483d7b,0xbd0ebd55,0x3d553d0e,0xbd7bbc48,
0x3d80,0xbcc4bd6d,0x3d353d35,0xbd6dbcc4,0xbd7b3c48,0x3d55bd0e,0xbd0e3d55,0x3c48bd7b,0xbd800000,0x3d6dbcc4,0xbd353d35,0x3cc4bd6d,0xbc48bd7b,0x3d0e3d55,0xbd55bd0e,0x3d7b3c48,
0x3d0ebd55,0x3d7b3c48,0x3c483d7b,0xbd553d0e,0xbd80,0x3d6dbcc4,0x3d353d35,0xbcc43d6d,0x3d553d0e,0xbc483d7b,0xbd7b3c48,0xbd0ebd55,0x3d800000,0x3cc43d6d,0xbd353d35,0xbd6dbcc4,
0xbd0e3d55,0xbd7bbc48,0xbc48bd7b,0x3d55bd0e,0x3d80,0xbd6d3cc4,0xbd35bd35,0x3cc4bd6d,0xbd55bd0e,0x3c48bd7b,0x3d7bbc48,0x3d0e3d55,0xbd800000,0xbcc4bd6d,0x3d35bd35,0x3d6d3cc4,
0x3d800000,0xbd353d35,0xbd80,0x3d353d35,0x3cc43d6d,0xbd6dbcc4,0x3d6dbcc4,0xbcc43d6d,0xbd800000,0x3d35bd35,0x3d80,0xbd35bd35,0xbcc4bd6d,0x3d6d3cc4,0xbd6d3cc4,0x3cc4bd6d,
0x3d800000,0xbd353d35,0xbd80,0x3d353d35,0x3cc43d6d,0xbd6dbcc4,0x3d6dbcc4,0xbcc43d6d,0xbd800000,0x3d35bd35,0x3d80,0xbd35bd35,0xbcc4bd6d,0x3d6d3cc4,0xbd6d3cc4,0x3cc4bd6d,
0x3d6d3cc4,0x3cc43d6d,0xbcc43d6d,0xbd6d3cc4,0x3d800000,0x3d353d35,0x3d80,0xbd353d35,0xbd6dbcc4,0xbcc4bd6d,0x3cc4bd6d,0x3d6dbcc4,0xbd800000,0xbd35bd35,0xbd80,0x3d35bd35,
0x3d6d3cc4,0x3cc43d6d,0xbcc43d6d,0xbd6d3cc4,0x3d800000,0x3d353d35,0x3d80,0xbd353d35,0xbd6dbcc4,0xbcc4bd6d,0x3cc4bd6d,0x3d6dbcc4,0xbd800000,0xbd35bd35,0xbd80,0x3d35bd35,
0xbd80,0x3d6d3cc4,0xbd353d35,0xbcc4bd6d,0x3d55bd0e,0x3c483d7b,0xbd7bbc48,0x3d0ebd55,0xbd800000,0x3cc4bd6d,0x3d353d35,0xbd6d3cc4,0xbd0ebd55,0x3d7bbc48,0xbc483d7b,0xbd55bd0e,
0x3d80,0xbd6dbcc4,0x3d35bd35,0x3cc43d6d,0xbd553d0e,0xbc48bd7b,0x3d7b3c48,0xbd0e3d55,0x3d800000,0xbcc43d6d,0xbd35bd35,0x3d6dbcc4,0x3d0e3d55,0xbd7b3c48,0x3c48bd7b,0x3d553d0e,
0x3c48bd7b,0x3d0ebd55,0x3d55bd0e,0x3d7bbc48,0xbd80,0x3cc4bd6d,0x3d35bd35,0x3d6dbcc4,0xbd7bbc48,0xbd55bd0e,0xbd0ebd55,0xbc48bd7b,0xbd800000,0xbd6dbcc4,0xbd35bd35,0xbcc4bd6d,
0xbc483d7b,0xbd0e3d55,0xbd553d0e,0xbd7b3c48,0x3d80,0xbcc43d6d,0xbd353d35,0xbd6d3cc4,0x3d7b3c48,0x3d553d0e,0x3d0e3d55,0x3c483d7b,0x3d800000,0x3d6d3cc4,0x3d353d35,0x3cc43d6d,
0x3d80,0x3d80,0x3d80,0x3d80,0x3d80,0x3d80,0x3d80,0x3d80,0x3d80,0x3d80,0x3d80,0x3d80,0x3d80,0x3d80,0x3d80,0x3d80,
0x3d80,0x3d80,0x3d80,0x3d80,0x3d80,0x3d80,0x3d80,0x3d80,0x3d80,0x3d80,0x3d80,0x3d80,0x3d80,0x3d80,0x3d80,0x3d80,
0xbd353d35,0xbd553d0e,0xbd6d3cc4,0xbd7b3c48,0x3d80,0xbc483d7b,0xbcc43d6d,0xbd0e3d55,0xbd35bd35,0xbd0ebd55,0xbcc4bd6d,0xbc48bd7b,0xbd800000,0xbd7bbc48,0xbd6dbcc4,0xbd55bd0e,
0x3d35bd35,0x3d55bd0e,0x3d6dbcc4,0x3d7bbc48,0xbd80,0x3c48bd7b,0x3cc4bd6d,0x3d0ebd55,0x3d353d35,0x3d0e3d55,0x3cc43d6d,0x3c483d7b,0x3d800000,0x3d7b3c48,0x3d6d3cc4,0x3d553d0e,
0xbd80,0x3cc4bd6d,0x3d35bd35,0x3d6dbcc4,0x3d800000,0x3d6d3cc4,0x3d353d35,0x3cc43d6d,0x3d80,0xbcc43d6d,0xbd353d35,0xbd6d3cc4,0xbd800000,0xbd6dbcc4,0xbd35bd35,0xbcc4bd6d,
0xbd80,0x3cc4bd6d,0x3d35bd35,0x3d6dbcc4,0x3d800000,0x3d6d3cc4,0x3d353d35,0x3cc43d6d,0x3d80,0xbcc43d6d,0xbd353d35,0xbd6d3cc4,0xbd800000,0xbd6dbcc4,0xbd35bd35,0xbcc4bd6d,
0xbd353d35,0xbd7b3c48,0xbd6dbcc4,0xbd0ebd55,0x3d800000,0x3d553d0e,0x3cc43d6d,0xbc483d7b,0xbd35bd35,0xbc48bd7b,0x3cc4bd6d,0x3d55bd0e,0x3d80,0xbd0e3d55,0xbd6d3cc4,0xbd7bbc48,
0x3d35bd35,0x3d7bbc48,0x3d6d3cc4,0x3d0e3d55,0xbd800000,0xbd55bd0e,0xbcc4bd6d,0x3c48bd7b,0x3d353d35,0x3c483d7b,0xbcc43d6d,0xbd553d0e,0xbd80,0x3d0ebd55,0x3d6dbcc4,0x3d7b3c48,
0x3d80,0xbd353d35,0xbd800000,0xbd35bd35,0xbd80,0x3d35bd35,0x3d800000,0x3d353d35,0x3d80,0xbd353d35,0xbd800000,0xbd35bd35,0xbd80,0x3d35bd35,0x3d800000,0x3d353d35,
0x3d80,0xbd353d35,0xbd800000,0xbd35bd35,0xbd80,0x3d35bd35,0x3d800000,0x3d353d35,0x3d80,0xbd353d35,0xbd800000,0xbd35bd35,0xbd80,0x3d35bd35,0x3d800000,0x3d353d35,
0xbd353d35,0xbd7bbc48,0xbcc4bd6d,0x3d0ebd55,0xbd80,0x3d55bd0e,0x3d6d3cc4,0x3c483d7b,0xbd35bd35,0x3c48bd7b,0x3d6dbcc4,0x3d553d0e,0x3d800000,0x3d0e3d55,0xbcc43d6d,0xbd7b3c48,
0x3d35bd35,0x3d7b3c48,0x3cc43d6d,0xbd0e3d55,0x3d80,0xbd553d0e,0xbd6dbcc4,0xbc48bd7b,0x3d353d35,0xbc483d7b,0xbd6d3cc4,0xbd55bd0e,0xbd800000,0xbd0ebd55,0x3cc4bd6d,0x3d7bbc48,
0xbd80,0x3d6dbcc4,0x3d353d35,0xbcc43d6d,0xbd800000,0xbcc4bd6d,0x3d35bd35,0x3d6d3cc4,0x3d80,0xbd6d3cc4,0xbd35bd35,0x3cc4bd6d,0x3d800000,0x3cc43d6d,0xbd353d35,0xbd6dbcc4,
0xbd80,0x3d6dbcc4,0x3d353d35,0xbcc43d6d,0xbd800000,0xbcc4bd6d,0x3d35bd35,0x3d6d3cc4,0x3d80,0xbd6d3cc4,0xbd35bd35,0x3cc4bd6d,0x3d800000,0x3cc43d6d,0xbd353d35,0xbd6dbcc4,
0xbd353d35,0xbd55bd0e,0x3cc4bd6d,0x3d7b3c48,0xbd800000,0xbc48bd7b,0x3d6dbcc4,0x3d0e3d55,0xbd35bd35,0x3d0ebd55,0x3d6d3cc4,0xbc483d7b,0xbd80,0x3d7bbc48,0x3cc43d6d,0xbd553d0e,
0x3d35bd35,0x3d553d0e,0xbcc43d6d,0xbd7bbc48,0x3d800000,0x3c483d7b,0xbd6d3cc4,0xbd0ebd55,0x3d353d35,0xbd0e3d55,0xbd6dbcc4,0x3c48bd7b,0x3d80,0xbd7b3c48,0xbcc4bd6d,0x3d55bd0e,
0xbd800000,0xbd800000,0xbd800000,0xbd800000,0xbd800000,0xbd800000,0xbd800000,0xbd800000,0xbd800000,0xbd800000,0xbd800000,0xbd800000,0xbd800000,0xbd800000,0xbd800000,0xbd800000,
0xbd800000,0xbd800000,0xbd800000,0xbd800000,0xbd800000,0xbd800000,0xbd800000,0xbd800000,0xbd800000,0xbd800000,0xbd800000,0xbd800000,0xbd800000,0xbd800000,0xbd800000,0xbd800000,
0xbd35bd35,0xbd0ebd55,0xbcc4bd6d,0xbc48bd7b,0xbd800000,0xbd7bbc48,0xbd6dbcc4,0xbd55bd0e,0x3d35bd35,0x3d55bd0e,0x3d6dbcc4,0x3d7bbc48,0x8000bd80,0x3c48bd7b,0x3cc4bd6d,0x3d0ebd55,
0x3d353d35,0x3d0e3d55,0x3cc43d6d,0x3c483d7b,0x3d800000,0x3d7b3c48,0x3d6d3cc4,0x3d553d0e,0xbd353d35,0xbd553d0e,0xbd6d3cc4,0xbd7b3c48,0x80003d80,0xbc483d7b,0xbcc43d6d,0xbd0e3d55,
0x3d800000,0x3d6d3cc4,0x3d353d35,0x3cc43d6d,0x80003d80,0xbcc43d6d,0xbd353d35,0xbd6d3cc4,0xbd800000,0xbd6dbcc4,0xbd35bd35,0xbcc4bd6d,0x8000bd80,0x3cc4bd6d,0x3d35bd35,0x3d6dbcc4,
0x3d800000,0x3d6d3cc4,0x3d353d35,0x3cc43d6d,0x80003d80,0xbcc43d6d,0xbd353d35,0xbd6d3cc4,0xbd800000,0xbd6dbcc4,0xbd35bd35,0xbcc4bd6d,0x8000bd80,0x3cc4bd6d,0x3d35bd35,0x3d6dbcc4,
0xbd35bd35,0xbc48bd7b,0x3cc4bd6d,0x3d55bd0e,0x80003d80,0xbd0e3d55,0xbd6d3cc4,0xbd7bbc48,0x3d35bd35,0x3d7bbc48,0x3d6d3cc4,0x3d0e3d55,0xbd800000,0xbd55bd0e,0xbcc4bd6d,0x3c48bd7b,
0x3d353d35,0x3c483d7b,0xbcc43d6d,0xbd553d0e,0x8000bd80,0x3d0ebd55,0x3d6dbcc4,0x3d7b3c48,0xbd353d35,0xbd7b3c48,0xbd6dbcc4,0xbd0ebd55,0x3d800000,0x3d553d0e,0x3cc43d6d,0xbc483d7b,
0xbd800000,0xbd35bd35,0x8000bd80,0x3d35bd35,0x3d800000,0x3d353d35,0x80003d80,0xbd353d35,0xbd800000,0xbd35bd35,0x8000bd80,0x3d35bd35,0x3d800000,0x3d353d35,0x80003d80,0xbd353d35,
0xbd800000,0xbd35bd35,0x8000bd80,0x3d35bd35,0x3d800000,0x3d353d35,0x80003d80,0xbd353d35,0xbd800000,0xbd35bd35,0x8000bd80,0x3d35bd35,0x3d800000,0x3d353d35,0x80003d80,0xbd353d35,
0xbd35bd35,0x3c48bd7b,0x3d6dbcc4,0x3d553d0e,0x3d800000,0x3d0e3d55,0xbcc43d6d,0xbd7b3c48,0x3d35bd35,0x3d7b3c48,0x3cc43d6d,0xbd0e3d55,0x80003d80,0xbd553d0e,0xbd6dbcc4,0xbc48bd7b,
0x3d353d35,0xbc483d7b,0xbd6d3cc4,0xbd55bd0e,0xbd800000,0xbd0ebd55,0x3cc4bd6d,0x3d7bbc48,0xbd353d35,0xbd7bbc48,0xbcc4bd6d,0x3d0ebd55,0x8000bd80,0x3d55bd0e,0x3d6d3cc4,0x3c483d7b,
0x3d800000,0x3cc43d6d,0xbd353d35,0xbd6dbcc4,0x8000bd80,0x3d6dbcc4,0x3d353d35,0xbcc43d6d,0xbd800000,0xbcc4bd6d,0x3d35bd35,0x3d6d3cc4,0x80003d80,0xbd6d3cc4,0xbd35bd35,0x3cc4bd6d,
0x3d800000,0x3cc43d6d,0xbd353d35,0xbd6dbcc4,0x8000bd80,0x3d6dbcc4,0x3d353d35,0xbcc43d6d,0xbd800000,0xbcc4bd6d,0x3d35bd35,0x3d6d3cc4,0x80003d80,0xbd6d3cc4,0xbd35bd35,0x3cc4bd6d,
0xbd35bd35,0x3d0ebd55,0x3d6d3cc4,0xbc483d7b,0x8000bd80,0x3d7bbc48,0x3cc43d6d,0xbd553d0e,0x3d35bd35,0x3d553d0e,0xbcc43d6d,0xbd7bbc48,0x3d800000,0x3c483d7b,0xbd6d3cc4,0xbd0ebd55,
0x3d353d35,0xbd0e3d55,0xbd6dbcc4,0x3c48bd7b,0x80003d80,0xbd7b3c48,0xbcc4bd6d,0x3d55bd0e,0xbd353d35,0xbd55bd0e,0x3cc4bd6d,0x3d7b3c48,0xbd800000,0xbc48bd7b,0x3d6dbcc4,0x3d0e3d55,
0x3d80,0xbd800000,0xbd80,0x3d800000,0x3d80,0xbd800000,0xbd80,0x3d800000,0x3d80,0xbd800000,0xbd80,0x3d800000,0x3d80,0xbd800000,0xbd80,0x3d800000,
0x3d80,0xbd800000,0xbd80,0x3d800000,0x3d80,0xbd800000,0xbd80,0x3d800000,0x3d80,0xbd800000,0xbd80,0x3d800000,0x3d80,0xbd800000,0xbd80,0x3d800000,
0xbd353d35,0xbd0ebd55,0x3d6dbcc4,0x3c483d7b,0x3d80,0xbd7bbc48,0x3cc4bd6d,0x3d553d0e,0xbd35bd35,0x3d55bd0e,0x3cc43d6d,0xbd7b3c48,0xbd800000,0x3c48bd7b,0x3d6d3cc4,0xbd0e3d55,
0x3d35bd35,0x3d0e3d55,0xbd6d3cc4,0xbc48bd7b,0xbd80,0x3d7b3c48,0xbcc43d6d,0xbd55bd0e,0x3d353d35,0xbd553d0e,0xbcc4bd6d,0x3d7bbc48,0x3d800000,0xbc483d7b,0xbd6dbcc4,0x3d0ebd55,
0xbd80,0x3d6d3cc4,0xbd353d35,0xbcc4bd6d,0x3d800000,0xbcc43d6d,0xbd35bd35,0x3d6dbcc4,0x3d80,0xbd6dbcc4,0x3d35bd35,0x3cc43d6d,0xbd800000,0x3cc4bd6d,0x3d353d35,0xbd6d3cc4,
0xbd80,0x3d6d3cc4,0xbd353d35,0xbcc4bd6d,0x3d800000,0xbcc43d6d,0xbd35bd35,0x3d6dbcc4,0x3d80,0xbd6dbcc4,0x3d35bd35,0x3cc43d6d,0xbd800000,0x3cc4bd6d,0x3d353d35,0xbd6d3cc4,
0xbd353d35,0xbc48bd7b,0x3d6d3cc4,0xbd553d0e,0x3d800000,0xbd0e3d55,0xbcc4bd6d,0x3d7b3c48,0xbd35bd35,0x3d7bbc48,0xbcc43d6d,0xbd0ebd55,0x3d80,0xbd55bd0e,0x3d6dbcc4,0xbc483d7b,
0x3d35bd35,0x3c483d7b,0xbd6dbcc4,0x3d55bd0e,0xbd800000,0x3d0ebd55,0x3cc43d6d,0xbd7bbc48,0x3d353d35,0xbd7b3c48,0x3cc4bd6d,0x3d0e3d55,0xbd80,0x3d553d0e,0xbd6d3cc4,0x3c48bd7b,
0x3d80,0xbd35bd35,0x3d800000,0xbd353d35,0xbd80,0x3d353d35,0xbd800000,0x3d35bd35,0x3d80,0xbd35bd35,0x3d800000,0xbd353d35,0xbd80,0x3d353d35,0xbd800000,0x3d35bd35,
0x3d80,0xbd35bd35,0x3d800000,0xbd353d35,0xbd80,0x3d353d35,0xbd800000,0x3d35bd35,0x3d80,0xbd35bd35,0x3d800000,0xbd353d35,0xbd80,0x3d353d35,0xbd800000,0x3d35bd35,
0xbd353d35,0x3c48bd7b,0x3cc43d6d,0xbd55bd0e,0xbd80,0x3d0e3d55,0xbd6dbcc4,0x3d7bbc48,0xbd35bd35,0x3d7b3c48,0xbd6d3cc4,0x3d0ebd55,0x3d800000,0xbd553d0e,0x3cc4bd6d,0x3c483d7b,
0x3d35bd35,0xbc483d7b,0xbcc4bd6d,0x3d553d0e,0x3d80,0xbd0ebd55,0x3d6d3cc4,0xbd7b3c48,0x3d353d35,0xbd7bbc48,0x3d6dbcc4,0xbd0e3d55,0xbd800000,0x3d55bd0e,0xbcc43d6d,0xbc48bd7b,
0xbd80,0x3cc43d6d,0xbd35bd35,0x3d6d3cc4,0xbd800000,0x3d6dbcc4,0xbd353d35,0x3cc4bd6d,0x3d80,0xbcc4bd6d,0x3d353d35,0xbd6dbcc4,0x3d800000,0xbd6d3cc4,0x3d35bd35,0xbcc43d6d,
0xbd80,0x3cc43d6d,0xbd35bd35,0x3d6d3cc4,0xbd800000,0x3d6dbcc4,0xbd353d35,0x3cc4bd6d,0x3d80,0xbcc4bd6d,0x3d353d35,0xbd6dbcc4,0x3d800000,0xbd6d3cc4,0x3d35bd35,0xbcc43d6d,
0xbd353d35,0x3d0ebd55,0xbcc43d6d,0x3c48bd7b,0xbd800000,0x3d7bbc48,0xbd6d3cc4,0x3d55bd0e,0xbd35bd35,0x3d553d0e,0xbd6dbcc4,0x3d7b3c48,0xbd80,0x3c483d7b,0xbcc4bd6d,0x3d0e3d55,
0x3d35bd35,0xbd0e3d55,0x3cc4bd6d,0xbc483d7b,0x3d800000,0xbd7b3c48,0x3d6dbcc4,0xbd553d0e,0x3d353d35,0xbd55bd0e,0x3d6d3cc4,0xbd7bbc48,0x3d80,0xbc48bd7b,0x3cc43d6d,0xbd0ebd55,
0xbd800000,0x8000bd80,0x3d800000,0x80003d80,0xbd800000,0x8000bd80,0x3d800000,0x80003d80,0xbd800000,0x8000bd80,0x3d800000,0x80003d80,0xbd800000,0x8000bd80,0x3d800000,0x80003d80,
0xbd800000,0x8000bd80,0x3d800000,0x80003d80,0xbd800000,0x8000bd80,0x3d800000,0x80003d80,0xbd800000,0x8000bd80,0x3d800000,0x80003d80,0xbd800000,0x8000bd80,0x3d800000,0x80003d80,
0xbd35bd35,0x3d55bd0e,0x3cc43d6d,0xbd7b3c48,0xbd800000,0x3c48bd7b,0x3d6d3cc4,0xbd0e3d55,0x3d35bd35,0x3d0e3d55,0xbd6d3cc4,0xbc48bd7b,0x8000bd80,0x3d7b3c48,0xbcc43d6d,0xbd55bd0e,
0x3d353d35,0xbd553d0e,0xbcc4bd6d,0x3d7bbc48,0x3d800000,0xbc483d7b,0xbd6dbcc4,0x3d0ebd55,0xbd353d35,0xbd0ebd55,0x3d6dbcc4,0x3c483d7b,0x80003d80,0xbd7bbc48,0x3cc4bd6d,0x3d553d0e,
0x3d800000,0xbcc43d6d,0xbd35bd35,0x3d6dbcc4,0x80003d80,0xbd6dbcc4,0x3d35bd35,0x3cc43d6d,0xbd800000,0x3cc4bd6d,0x3d353d35,0xbd6d3cc4,0x8000bd80,0x3d6d3cc4,0xbd353d35,0xbcc4bd6d,
0x3d800000,0xbcc43d6d,0xbd35bd35,0x3d6dbcc4,0x80003d80,0xbd6dbcc4,0x3d35bd35,0x3cc43d6d,0xbd800000,0x3cc4bd6d,0x3d353d35,0xbd6d3cc4,0x8000bd80,0x3d6d3cc4,0xbd353d35,0xbcc4bd6d,
0xbd35bd35,0x3d7bbc48,0xbcc43d6d,0xbd0ebd55,0x80003d80,0xbd55bd0e,0x3d6dbcc4,0xbc483d7b,0x3d35bd35,0x3c483d7b,0xbd6dbcc4,0x3d55bd0e,0xbd800000,0x3d0ebd55,0x3cc43d6d,0xbd7bbc48,
0x3d353d35,0xbd7b3c48,0x3cc4bd6d,0x3d0e3d55,0x8000bd80,0x3d553d0e,0xbd6d3cc4,0x3c48bd7b,0xbd353d35,0xbc48bd7b,0x3d6d3cc4,0xbd553d0e,0x3d800000,0xbd0e3d55,0xbcc4bd6d,0x3d7b3c48,
0xbd800000,0x3d35bd35,0x80003d80,0xbd35bd35,0x3d800000,0xbd353d35,0x8000bd80,0x3d353d35,0xbd800000,0x3d35bd35,0x80003d80,0xbd35bd35,0x3d800000,0xbd353d35,0x8000bd80,0x3d353d35,
0xbd800000,0x3d35bd35,0x80003d80,0xbd35bd35,0x3d800000,0xbd353d35,0x8000bd80,0x3d353d35,0xbd800000,0x3d35bd35,0x80003d80,0xbd35bd35,0x3d800000,0xbd353d35,0x8000bd80,0x3d353d35,
0xbd35bd35,0x3d7b3c48,0xbd6d3cc4,0x3d0ebd55,0x3d800000,0xbd553d0e,0x3cc4bd6d,0x3c483d7b,0x3d35bd35,0xbc483d7b,0xbcc4bd6d,0x3d553d0e,0x80003d80,0xbd0ebd55,0x3d6d3cc4,0xbd7b3c48,
0x3d353d35,0xbd7bbc48,0x3d6dbcc4,0xbd0e3d55,0xbd800000,0x3d55bd0e,0xbcc43d6d,0xbc48bd7b,0xbd353d35,0x3c48bd7b,0x3cc43d6d,0xbd55bd0e,0x8000bd80,0x3d0e3d55,0xbd6dbcc4,0x3d7bbc48,
0x3d800000,0xbd6d3cc4,0x3d35bd35,0xbcc43d6d,0x8000bd80,0x3cc43d6d,0xbd35bd35,0x3d6d3cc4,0xbd800000,0x3d6dbcc4,0xbd353d35,0x3cc4bd6d,0x80003d80,0xbcc4bd6d,0x3d353d35,0xbd6dbcc4,
0x3d800000,0xbd6d3cc4,0x3d35bd35,0xbcc43d6d,0x8000bd80,0x3cc43d6d,0xbd35bd35,0x3d6d3cc4,0xbd800000,0x3d6dbcc4,0xbd353d35,0x3cc4bd6d,0x80003d80,0xbcc4bd6d,0x3d353d35,0xbd6dbcc4,
0xbd35bd35,0x3d553d0e,0xbd6dbcc4,0x3d7b3c48,0x8000bd80,0x3c483d7b,0xbcc4bd6d,0x3d0e3d55,0x3d35bd35,0xbd0e3d55,0x3cc4bd6d,0xbc483d7b,0x3d800000,0xbd7b3c48,0x3d6dbcc4,0xbd553d0e,
0x3d353d35,0xbd55bd0e,0x3d6d3cc4,0xbd7bbc48,0x80003d80,0xbc48bd7b,0x3cc43d6d,0xbd0ebd55,0xbd353d35,0x3d0ebd55,0xbcc43d6d,0x3c48bd7b,0xbd800000,0x3d7bbc48,0xbd6d3cc4,0x3d55bd0e,
0x3d80,0xbd80,0x3d80,0xbd80,0x3d80,0xbd80,0x3d80,0xbd80,0x3d80,0xbd80,0x3d80,0xbd80,0x3d80,0xbd80,0x3d80,0xbd80,
0x3d80,0xbd80,0x3d80,0xbd80,0x3d80,0xbd80,0x3d80,0xbd80,0x3d80,0xbd80,0x3d80,0xbd80,0x3d80,0xbd80,0x3d80,0xbd80,
0xbd353d35,0x3d55bd0e,0xbd6d3cc4,0x3d7bbc48,0x3d80,0x3c48bd7b,0xbcc43d6d,0x3d0ebd55,0xbd35bd35,0x3d0e3d55,0xbcc4bd6d,0x3c483d7b,0xbd800000,0x3d7b3c48,0xbd6dbcc4,0x3d553d0e,
0x3d35bd35,0xbd553d0e,0x3d6dbcc4,0xbd7b3c48,0xbd80,0xbc483d7b,0x3cc4bd6d,0xbd0e3d55,0x3d353d35,0xbd0ebd55,0x3cc43d6d,0xbc48bd7b,0x3d800000,0xbd7bbc48,0x3d6d3cc4,0xbd55bd0e,
0xbd80,0xbcc43d6d,0x3d35bd35,0xbd6d3cc4,0x3d800000,0xbd6dbcc4,0x3d353d35,0xbcc4bd6d,0x3d80,0x3cc4bd6d,0xbd353d35,0x3d6dbcc4,0xbd800000,0x3d6d3cc4,0xbd35bd35,0x3cc43d6d,
0xbd80,0xbcc43d6d,0x3d35bd35,0xbd6d3cc4,0x3d800000,0xbd6dbcc4,0x3d353d35,0xbcc4bd6d,0x3d80,0x3cc4bd6d,0xbd353d35,0x3d6dbcc4,0xbd800000,0x3d6d3cc4,0xbd35bd35,0x3cc43d6d,
0xbd353d35,0x3d7bbc48,0xbd6dbcc4,0x3d0e3d55,0x3d800000,0xbd55bd0e,0x3cc43d6d,0x3c48bd7b,0xbd35bd35,0x3c483d7b,0x3cc4bd6d,0xbd553d0e,0x3d80,0x3d0ebd55,0xbd6d3cc4,0x3d7b3c48,
0x3d35bd35,0xbd7b3c48,0x3d6d3cc4,0xbd0ebd55,0xbd800000,0x3d553d0e,0xbcc4bd6d,0xbc483d7b,0x3d353d35,0xbc48bd7b,0xbcc43d6d,0x3d55bd0e,0xbd80,0xbd0e3d55,0x3d6dbcc4,0xbd7bbc48,
0x3d80,0x3d35bd35,0xbd800000,0x3d353d35,0xbd80,0xbd353d35,0x3d800000,0xbd35bd35,0x3d80,0x3d35bd35,0xbd800000,0x3d353d35,0xbd80,0xbd353d35,0x3d800000,0xbd35bd35,
0x3d80,0x3d35bd35,0xbd800000,0x3d353d35,0xbd80,0xbd353d35,0x3d800000,0xbd35bd35,0x3d80,0x3d35bd35,0xbd800000,0x3d353d35,0xbd80,0xbd353d35,0x3d800000,0xbd35bd35,
0xbd353d35,0x3d7b3c48,0xbcc4bd6d,0xbd0e3d55,0xbd80,0xbd553d0e,0x3d6d3cc4,0xbc48bd7b,0xbd35bd35,0xbc483d7b,0x3d6dbcc4,0xbd55bd0e,0x3d800000,0xbd0ebd55,0xbcc43d6d,0x3d7bbc48,
0x3d35bd35,0xbd7bbc48,0x3cc43d6d,0x3d0ebd55,0x3d80,0x3d55bd0e,0xbd6dbcc4,0x3c483d7b,0x3d353d35,0x3c48bd7b,0xbd6d3cc4,0x3d553d0e,0xbd800000,0x3d0e3d55,0x3cc4bd6d,0xbd7b3c48,
0xbd80,0xbd6d3cc4,0x3d353d35,0x3cc4bd6d,0xbd800000,0x3cc43d6d,0x3d35bd35,0xbd6dbcc4,0x3d80,0x3d6dbcc4,0xbd35bd35,0xbcc43d6d,0x3d800000,0xbcc4bd6d,0xbd353d35,0x3d6d3cc4,
0xbd80,0xbd6d3cc4,0x3d353d35,0x3cc4bd6d,0xbd800000,0x3cc43d6d,0x3d35bd35,0xbd6dbcc4,0x3d80,0x3d6dbcc4,0xbd35bd35,0xbcc43d6d,0x3d800000,0xbcc4bd6d,0xbd353d35,0x3d6d3cc4,
0xbd353d35,0x3d553d0e,0x3cc4bd6d,0xbd7bbc48,0xbd800000,0x3c483d7b,0x3d6dbcc4,0xbd0ebd55,0xbd35bd35,0xbd0e3d55,0x3d6d3cc4,0x3c48bd7b,0xbd80,0xbd7b3c48,0x3cc43d6d,0x3d55bd0e,
0x3d35bd35,0xbd55bd0e,0xbcc43d6d,0x3d7b3c48,0x3d800000,0xbc48bd7b,0xbd6d3cc4,0x3d0e3d55,0x3d353d35,0x3d0ebd55,0xbd6dbcc4,0xbc483d7b,0x3d80,0x3d7bbc48,0xbcc4bd6d,0xbd553d0e,
0xbd800000,0x3d800000,0xbd800000,0x3d800000,0xbd800000,0x3d800000,0xbd800000,0x3d800000,0xbd800000,0x3d800000,0xbd800000,0x3d800000,0xbd800000,0x3d800000,0xbd800000,0x3d800000,
0xbd800000,0x3d800000,0xbd800000,0x3d800000,0xbd800000,0x3d800000,0xbd800000,0x3d800000,0xbd800000,0x3d800000,0xbd800000,0x3d800000,0xbd800000,0x3d800000,0xbd800000,0x3d800000,
0xbd35bd35,0x3d0e3d55,0xbcc4bd6d,0x3c483d7b,0xbd800000,0x3d7b3c48,0xbd6dbcc4,0x3d553d0e,0x3d35bd35,0xbd553d0e,0x3d6dbcc4,0xbd7b3c48,0x8000bd80,0xbc483d7b,0x3cc4bd6d,0xbd0e3d55,
0x3d353d35,0xbd0ebd55,0x3cc43d6d,0xbc48bd7b,0x3d800000,0xbd7bbc48,0x3d6d3cc4,0xbd55bd0e,0xbd353d35,0x3d55bd0e,0xbd6d3cc4,0x3d7bbc48,0x80003d80,0x3c48bd7b,0xbcc43d6d,0x3d0ebd55,
0x3d800000,0xbd6dbcc4,0x3d353d35,0xbcc4bd6d,0x80003d80,0x3cc4bd6d,0xbd353d35,0x3d6dbcc4,0xbd800000,0x3d6d3cc4,0xbd35bd35,0x3cc43d6d,0x8000bd80,0xbcc43d6d,0x3d35bd35,0xbd6d3cc4,
0x3d800000,0xbd6dbcc4,0x3d353d35,0xbcc4bd6d,0x80003d80,0x3cc4bd6d,0xbd353d35,0x3d6dbcc4,0xbd800000,0x3d6d3cc4,0xbd35bd35,0x3cc43d6d,0x8000bd80,0xbcc43d6d,0x3d35bd35,0xbd6d3cc4,
0xbd35bd35,0x3c483d7b,0x3cc4bd6d,0xbd553d0e,0x80003d80,0x3d0ebd55,0xbd6d3cc4,0x3d7b3c48,0x3d35bd35,0xbd7b3c48,0x3d6d3cc4,0xbd0ebd55,0xbd800000,0x3d553d0e,0xbcc4bd6d,0xbc483d7b,
0x3d353d35,0xbc48bd7b,0xbcc43d6d,0x3d55bd0e,0x8000bd80,0xbd0e3d55,0x3d6dbcc4,0xbd7bbc48,0xbd353d35,0x3d7bbc48,0xbd6dbcc4,0x3d0e3d55,0x3d800000,0xbd55bd0e,0x3cc43d6d,0x3c48bd7b,
0xbd800000,0x3d353d35,0x8000bd80,0xbd353d35,0x3d800000,0xbd35bd35,0x80003d80,0x3d35bd35,0xbd800000,0x3d353d35,0x8000bd80,0xbd353d35,0x3d800000,0xbd35bd35,0x80003d80,0x3d35bd35,
0xbd800000,0x3d353d35,0x8000bd80,0xbd353d35,0x3d800000,0xbd35bd35,0x80003d80,0x3d35bd35,0xbd800000,0x3d353d35,0x8000bd80,0xbd353d35,0x3d800000,0xbd35bd35,0x80003d80,0x3d35bd35,
0xbd35bd35,0xbc483d7b,0x3d6dbcc4,0xbd55bd0e,0x3d800000,0xbd0ebd55,0xbcc43d6d,0x3d7bbc48,0x3d35bd35,0xbd7bbc48,0x3cc43d6d,0x3d0ebd55,0x80003d80,0x3d55bd0e,0xbd6dbcc4,0x3c483d7b,
0x3d353d35,0x3c48bd7b,0xbd6d3cc4,0x3d553d0e,0xbd800000,0x3d0e3d55,0x3cc4bd6d,0xbd7b3c48,0xbd353d35,0x3d7b3c48,0xbcc4bd6d,0xbd0e3d55,0x8000bd80,0xbd553d0e,0x3d6d3cc4,0xbc48bd7b,
0x3d800000,0xbcc4bd6d,0xbd353d35,0x3d6d3cc4,0x8000bd80,0xbd6d3cc4,0x3d353d35,0x3cc4bd6d,0xbd800000,0x3cc43d6d,0x3d35bd35,0xbd6dbcc4,0x80003d80,0x3d6dbcc4,0xbd35bd35,0xbcc43d6d,
0x3d800000,0xbcc4bd6d,0xbd353d35,0x3d6d3cc4,0x8000bd80,0xbd6d3cc4,0x3d353d35,0x3cc4bd6d,0xbd800000,0x3cc43d6d,0x3d35bd35,0xbd6dbcc4,0x80003d80,0x3d6dbcc4,0xbd35bd35,0xbcc43d6d,
0xbd35bd35,0xbd0e3d55,0x3d6d3cc4,0x3c48bd7b,0x8000bd80,0xbd7b3c48,0x3cc43d6d,0x3d55bd0e,0x3d35bd35,0xbd55bd0e,0xbcc43d6d,0x3d7b3c48,0x3d800000,0xbc48bd7b,0xbd6d3cc4,0x3d0e3d55,
0x3d353d35,0x3d0ebd55,0xbd6dbcc4,0xbc483d7b,0x80003d80,0x3d7bbc48,0xbcc4bd6d,0xbd553d0e,0xbd353d35,0x3d553d0e,0x3cc4bd6d,0xbd7bbc48,0xbd800000,0x3c483d7b,0x3d6dbcc4,0xbd0ebd55,
0x3d80,0x3d800000,0xbd80,0xbd800000,0x3d80,0x3d800000,0xbd80,0xbd800000,0x3d80,0x3d800000,0xbd80,0xbd800000,0x3d80,0x3d800000,0xbd80,0xbd800000,
0x3d80,0x3d800000,0xbd80,0xbd800000,0x3d80,0x3d800000,0xbd80,0xbd800000,0x3d80,0x3d800000,0xbd80,0xbd800000,0x3d80,0x3d800000,0xbd80,0xbd800000,
0xbd353d35,0x3d0e3d55,0x3d6dbcc4,0xbc48bd7b,0x3d80,0x3d7b3c48,0x3cc4bd6d,0xbd55bd0e,0xbd35bd35,0xbd553d0e,0x3cc43d6d,0x3d7bbc48,0xbd800000,0xbc483d7b,0x3d6d3cc4,0x3d0ebd55,
0x3d35bd35,0xbd0ebd55,0xbd6d3cc4,0x3c483d7b,0xbd80,0xbd7bbc48,0xbcc43d6d,0x3d553d0e,0x3d353d35,0x3d55bd0e,0xbcc4bd6d,0xbd7b3c48,0x3d800000,0x3c48bd7b,0xbd6dbcc4,0xbd0e3d55,
0xbd80,0xbd6dbcc4,0xbd353d35,0x3cc43d6d,0x3d800000,0x3cc4bd6d,0xbd35bd35,0xbd6d3cc4,0x3d80,0x3d6d3cc4,0x3d35bd35,0xbcc4bd6d,0xbd800000,0xbcc43d6d,0x3d353d35,0x3d6dbcc4,
0xbd80,0xbd6dbcc4,0xbd353d35,0x3cc43d6d,0x3d800000,0x3cc4bd6d,0xbd35bd35,0xbd6d3cc4,0x3d80,0x3d6d3cc4,0x3d35bd35,0xbcc4bd6d,0xbd800000,0xbcc43d6d,0x3d353d35,0x3d6dbcc4,
0xbd353d35,0x3c483d7b,0x3d6d3cc4,0x3d55bd0e,0x3d800000,0x3d0ebd55,0xbcc4bd6d,0xbd7bbc48,0xbd35bd35,0xbd7b3c48,0xbcc43d6d,0x3d0e3d55,0x3d80,0x3d553d0e,0x3d6dbcc4,0x3c48bd7b,
0x3d35bd35,0xbc48bd7b,0xbd6dbcc4,0xbd553d0e,0xbd800000,0xbd0e3d55,0x3cc43d6d,0x3d7b3c48,0x3d353d35,0x3d7bbc48,0x3cc4bd6d,0xbd0ebd55,0xbd80,0xbd55bd0e,0xbd6d3cc4,0xbc483d7b,
0x3d80,0x3d353d35,0x3d800000,0x3d35bd35,0xbd80,0xbd35bd35,0xbd800000,0xbd353d35,0x3d80,0x3d353d35,0x3d800000,0x3d35bd35,0xbd80,0xbd35bd35,0xbd800000,0xbd353d35,
0x3d80,0x3d353d35,0x3d800000,0x3d35bd35,0xbd80,0xbd35bd35,0xbd800000,0xbd353d35,0x3d80,0x3d353d35,0x3d800000,0x3d35bd35,0xbd80,0xbd35bd35,0xbd800000,0xbd353d35,
0xbd353d35,0xbc483d7b,0x3cc43d6d,0x3d553d0e,0xbd80,0xbd0ebd55,0xbd6dbcc4,0xbd7b3c48,0xbd35bd35,0xbd7bbc48,0xbd6d3cc4,0xbd0e3d55,0x3d800000,0x3d55bd0e,0x3cc4bd6d,0xbc48bd7b,
0x3d35bd35,0x3c48bd7b,0xbcc4bd6d,0xbd55bd0e,0x3d80,0x3d0e3d55,0x3d6d3cc4,0x3d7bbc48,0x3d353d35,0x3d7b3c48,0x3d6dbcc4,0x3d0ebd55,0xbd800000,0xbd553d0e,0xbcc43d6d,0x3c483d7b,
0xbd80,0xbcc4bd6d,0xbd35bd35,0xbd6dbcc4,0xbd800000,0xbd6d3cc4,0xbd353d35,0xbcc43d6d,0x3d80,0x3cc43d6d,0x3d353d35,0x3d6d3cc4,0x3d800000,0x3d6dbcc4,0x3d35bd35,0x3cc4bd6d,
0xbd80,0xbcc4bd6d,0xbd35bd35,0xbd6dbcc4,0xbd800000,0xbd6d3cc4,0xbd353d35,0xbcc43d6d,0x3d80,0x3cc43d6d,0x3d353d35,0x3d6d3cc4,0x3d800000,0x3d6dbcc4,0x3d35bd35,0x3cc4bd6d,
0xbd353d35,0xbd0e3d55,0xbcc43d6d,0xbc483d7b,0xbd800000,0xbd7b3c48,0xbd6d3cc4,0xbd553d0e,0xbd35bd35,0xbd55bd0e,0xbd6dbcc4,0xbd7bbc48,0xbd80,0xbc48bd7b,0xbcc4bd6d,0xbd0ebd55,
0x3d35bd35,0x3d0ebd55,0x3cc4bd6d,0x3c48bd7b,0x3d800000,0x3d7bbc48,0x3d6dbcc4,0x3d55bd0e,0x3d353d35,0x3d553d0e,0x3d6d3cc4,0x3d7b3c48,0x3d80,0x3c483d7b,0x3cc43d6d,0x3d0e3d55,
0xbd800000,0x80003d80,0x3d800000,0x8000bd80,0xbd800000,0x80003d80,0x3d800000,0x8000bd80,0xbd800000,0x80003d80,0x3d800000,0x8000bd80,0xbd800000,0x80003d80,0x3d800000,0x8000bd80,
0xbd800000,0x80003d80,0x3d800000,0x8000bd80,0xbd800000,0x80003d80,0x3d800000,0x8000bd80,0xbd800000,0x80003d80,0x3d800000,0x8000bd80,0xbd800000,0x80003d80,0x3d800000,0x8000bd80,
0xbd35bd35,0xbd553d0e,0x3cc43d6d,0x3d7bbc48,0xbd800000,0xbc483d7b,0x3d6d3cc4,0x3d0ebd55,0x3d35bd35,0xbd0ebd55,0xbd6d3cc4,0x3c483d7b,0x8000bd80,0xbd7bbc48,0xbcc43d6d,0x3d553d0e,
0x3d353d35,0x3d55bd0e,0xbcc4bd6d,0xbd7b3c48,0x3d800000,0x3c48bd7b,0xbd6dbcc4,0xbd0e3d55,0xbd353d35,0x3d0e3d55,0x3d6dbcc4,0xbc48bd7b,0x80003d80,0x3d7b3c48,0x3cc4bd6d,0xbd55bd0e,
0x3d800000,0x3cc4bd6d,0xbd35bd35,0xbd6d3cc4,0x80003d80,0x3d6d3cc4,0x3d35bd35,0xbcc4bd6d,0xbd800000,0xbcc43d6d,0x3d353d35,0x3d6dbcc4,0x8000bd80,0xbd6dbcc4,0xbd353d35,0x3cc43d6d,
0x3d800000,0x3cc4bd6d,0xbd35bd35,0xbd6d3cc4,0x80003d80,0x3d6d3cc4,0x3d35bd35,0xbcc4bd6d,0xbd800000,0xbcc43d6d,0x3d353d35,0x3d6dbcc4,0x8000bd80,0xbd6dbcc4,0xbd353d35,0x3cc43d6d,
0xbd35bd35,0xbd7b3c48,0xbcc43d6d,0x3d0e3d55,0x80003d80,0x3d553d0e,0x3d6dbcc4,0x3c48bd7b,0x3d35bd35,0xbc48bd7b,0xbd6dbcc4,0xbd553d0e,0xbd800000,0xbd0e3d55,0x3cc43d6d,0x3d7b3c48,
0x3d353d35,0x3d7bbc48,0x3cc4bd6d,0xbd0ebd55,0x8000bd80,0xbd55bd0e,0xbd6d3cc4,0xbc483d7b,0xbd353d35,0x3c483d7b,0x3d6d3cc4,0x3d55bd0e,0x3d800000,0x3d0ebd55,0xbcc4bd6d,0xbd7bbc48,
0xbd800000,0xbd353d35,0x80003d80,0x3d353d35,0x3d800000,0x3d35bd35,0x8000bd80,0xbd35bd35,0xbd800000,0xbd353d35,0x80003d80,0x3d353d35,0x3d800000,0x3d35bd35,0x8000bd80,0xbd35bd35,
0xbd800000,0xbd353d35,0x80003d80,0x3d353d35,0x3d800000,0x3d35bd35,0x8000bd80,0xbd35bd35,0xbd800000,0xbd353d35,0x80003d80,0x3d353d35,0x3d800000,0x3d35bd35,0x8000bd80,0xbd35bd35,
0xbd35bd35,0xbd7bbc48,0xbd6d3cc4,0xbd0e3d55,0x3d800000,0x3d55bd0e,0x3cc4bd6d,0xbc48bd7b,0x3d35bd35,0x3c48bd7b,0xbcc4bd6d,0xbd55bd0e,0x80003d80,0x3d0e3d55,0x3d6d3cc4,0x3d7bbc48,
0x3d353d35,0x3d7b3c48,0x3d6dbcc4,0x3d0ebd55,0xbd800000,0xbd553d0e,0xbcc43d6d,0x3c483d7b,0xbd353d35,0xbc483d7b,0x3cc43d6d,0x3d553d0e,0x8000bd80,0xbd0ebd55,0xbd6dbcc4,0xbd7b3c48,
0x3d800000,0x3d6dbcc4,0x3d35bd35,0x3cc4bd6d,0x8000bd80,0xbcc4bd6d,0xbd35bd35,0xbd6dbcc4,0xbd800000,0xbd6d3cc4,0xbd353d35,0xbcc43d6d,0x80003d80,0x3cc43d6d,0x3d353d35,0x3d6d3cc4,
0x3d800000,0x3d6dbcc4,0x3d35bd35,0x3cc4bd6d,0x8000bd80,0xbcc4bd6d,0xbd35bd35,0xbd6dbcc4,0xbd800000,0xbd6d3cc4,0xbd353d35,0xbcc43d6d,0x80003d80,0x3cc43d6d,0x3d353d35,0x3d6d3cc4,
0xbd35bd35,0xbd55bd0e,0xbd6dbcc4,0xbd7bbc48,0x8000bd80,0xbc48bd7b,0xbcc4bd6d,0xbd0ebd55,0x3d35bd35,0x3d0ebd55,0x3cc4bd6d,0x3c48bd7b,0x3d800000,0x3d7bbc48,0x3d6dbcc4,0x3d55bd0e,
0x3d353d35,0x3d553d0e,0x3d6d3cc4,0x3d7b3c48,0x80003d80,0x3c483d7b,0x3cc43d6d,0x3d0e3d55,0xbd353d35,0xbd0e3d55,0xbcc43d6d,0xbc483d7b,0xbd800000,0xbd7b3c48,0xbd6d3cc4,0xbd553d0e,
0x3d80,0xbb493d80,0xbbc93d7f,0xbc163d7d,0xbc483d7b,0xbc793d78,0xbc953d75,0xbcac3d71,0xbcc43d6d,0xbcdb3d67,0xbcf13d62,0xbd043d5c,0xbd0e3d55,0xbd183d4e,0xbd223d46,0xbd2c3d3e,
0xbd353d35,0xbd3e3d2c,0xbd463d22,0xbd4e3d18,0xbd553d0e,0xbd5c3d04,0xbd623cf1,0xbd673cdb,0xbd6d3cc4,0xbd713cac,0xbd753c95,0xbd783c79,0xbd7b3c48,0xbd7d3c16,0xbd7f3bc9,0xbd803b49,
0xbd553d0e,0xbd713cac,0xbd7f3bc9,0xbd7dbc16,0x3d80,0xbc793d78,0xbcf13d62,0xbd2c3d3e,0xbc48bd7b,0x3b49bd80,0x3c95bd75,0x3d04bd5c,0xbd6dbcc4,0xbd4ebd18,0xbd22bd46,0xbcdbbd67,
0x3d7b3c48,0x3d673cdb,0x3d463d22,0x3d183d4e,0x3d35bd35,0x3d5cbd04,0x3d75bc95,0x3d80bb49,0xbd0e3d55,0xbd3e3d2c,0xbd623cf1,0xbd783c79,0x3cc43d6d,0x3c163d7d,0xbbc93d7f,0xbcac3d71,
0x3cc4bd6d,0x3d3ebd2c,0x3d75bc95,0x3d7d3c16,0x3d553d0e,0x3d043d5c,0x3bc93d7f,0xbcac3d71,0x3d80,0xbcdb3d67,0xbd463d22,0xbd783c79,0xbd7bbc48,0xbd4ebd18,0xbcf1bd62,0xbb49bd80,
0x3d6dbcc4,0x3d803b49,0x3d623cf1,0x3d183d4e,0x3c483d7b,0xbc793d78,0xbd223d46,0xbd673cdb,0xbd353d35,0xbd713cac,0xbd7fbbc9,0xbd5cbd04,0xbd0ebd55,0xbc16bd7d,0x3c95bd75,0x3d2cbd3e,
0xbd7b3c48,0xbd67bcdb,0xbcf1bd62,0x3c16bd7d,0x3d6d3cc4,0x3d043d5c,0xbbc93d7f,0xbd2c3d3e,0xbd0ebd55,0x3b49bd80,0x3d22bd46,0x3d78bc79,0x3d80,0xbd183d4e,0xbd753c95,0xbd71bcac,
0x3d553d0e,0x3cac3d71,0xbc953d75,0xbd4e3d18,0xbcc4bd6d,0x3c79bd78,0x3d46bd22,0x3d80bb49,0xbc483d7b,0xbd3e3d2c,0xbd7f3bc9,0xbd5cbd04,0x3d35bd35,0x3d7dbc16,0x3d623cf1,0x3cdb3d67,
0xbd353d35,0xbd80bb49,0xbd22bd46,0x3c16bd7d,0x3d55bd0e,0x3d783c79,0x3cf13d62,0xbcac3d71,0xbd6d3cc4,0xbd67bcdb,0xbc95bd75,0x3d04bd5c,0x3d7bbc48,0x3d4e3d18,0x3bc93d7f,0xbd2c3d3e,
0x3d80,0xbd3e3d2c,0xbd7fbbc9,0xbd18bd4e,0x3c48bd7b,0x3d5cbd04,0x3d753c95,0x3cdb3d67,0xbcc43d6d,0xbd713cac,0xbd62bcf1,0xbc79bd78,0x3d0ebd55,0x3d7dbc16,0x3d463d22,0x3b493d80,
0xbd7bbc48,0xbcacbd71,0x3d22bd46,0x3d7d3c16,0x3d35bd35,0x3d783c79,0x3c953d75,0xbd2c3d3e,0x3d0ebd55,0x3d803b49,0x3cf13d62,0xbd043d5c,0x3cc43d6d,0xbd183d4e,0xbd7fbbc9,0xbcdbbd67,
0x3d55bd0e,0x3d673cdb,0x3bc93d7f,0xbd4e3d18,0x3d80,0xbd5c3d04,0xbd62bcf1,0xbb49bd80,0x3c483d7b,0xbd3e3d2c,0xbd75bc95,0xbc79bd78,0xbd6dbcc4,0xbc16bd7d,0x3d46bd22,0x3d713cac,
0x3d6dbcc4,0x3d2c3d3e,0xbcf13d62,0xbd7dbc16,0xbc48bd7b,0x3d5cbd04,0x3d463d22,0xbcac3d71,0xbd353d35,0xbd67bcdb,0x3bc9bd7f,0x3d78bc79,0x3d0e3d55,0xbd183d4e,0xbd75bc95,0xbb49bd80,
0x3cc4bd6d,0x3d803b49,0x3c953d75,0xbd4e3d18,0xbd55bd0e,0x3c79bd78,0x3d7fbbc9,0x3cdb3d67,0x3d80,0xbd713cac,0xbd22bd46,0x3d04bd5c,0x3d7b3c48,0x3c163d7d,0xbd623cf1,0xbd3ebd2c,
0xbd55bd0e,0x3cdbbd67,0x3d753c95,0xbc163d7d,0xbcc4bd6d,0x3d5cbd04,0x3d223d46,0xbd2c3d3e,0x3c48bd7b,0x3d803b49,0x3bc93d7f,0xbd783c79,0x3d35bd35,0x3d4e3d18,0xbcf13d62,0xbd71bcac,
0x3d7bbc48,0x3cac3d71,0xbd623cf1,0xbd18bd4e,0x3d6d3cc4,0xbc793d78,0xbd7fbbc9,0xbb49bd80,0x3d0e3d55,0xbd3e3d2c,0xbd46bd22,0x3d04bd5c,0x3d80,0xbd7d3c16,0xbc95bd75,0x3d67bcdb,
0xbd800000,0xbd80bb49,0xbd7fbbc9,0xbd7dbc16,0xbd7bbc48,0xbd78bc79,0xbd75bc95,0xbd71bcac,0xbd6dbcc4,0xbd67bcdb,0xbd62bcf1,0xbd5cbd04,0xbd55bd0e,0xbd4ebd18,0xbd46bd22,0xbd3ebd2c,
0xbd35bd35,0xbd2cbd3e,0xbd22bd46,0xbd18bd4e,0xbd0ebd55,0xbd04bd5c,0xbcf1bd62,0xbcdbbd67,0xbcc4bd6d,0xbcacbd71,0xbc95bd75,0xbc79bd78,0xbc48bd7b,0xbc16bd7d,0xbbc9bd7f,0xbb49bd80,
0xbd0ebd55,0xbcacbd71,0xbbc9bd7f,0x3c16bd7d,0xbd800000,0xbd78bc79,0xbd62bcf1,0xbd3ebd2c,0x3d7bbc48,0x3d803b49,0x3d753c95,0x3d5c3d04,0x3cc4bd6d,0x3d18bd4e,0x3d46bd22,0x3d67bcdb,
0xbc483d7b,0xbcdb3d67,0xbd223d46,0xbd4e3d18,0x3d353d35,0x3d043d5c,0x3c953d75,0x3b493d80,0xbd55bd0e,0xbd2cbd3e,0xbcf1bd62,0xbc79bd78,0xbd6d3cc4,0xbd7d3c16,0xbd7fbbc9,0xbd71bcac,
0x3d6d3cc4,0x3d2c3d3e,0x3c953d75,0xbc163d7d,0xbd0e3d55,0xbd5c3d04,0xbd7f3bc9,0xbd71bcac,0xbd800000,0xbd67bcdb,0xbd22bd46,0xbc79bd78,0x3c48bd7b,0x3d18bd4e,0x3d62bcf1,0x3d80bb49,
0x3cc43d6d,0xbb493d80,0xbcf13d62,0xbd4e3d18,0xbd7b3c48,0xbd78bc79,0xbd46bd22,0xbcdbbd67,0xbd35bd35,0xbcacbd71,0x3bc9bd7f,0x3d04bd5c,0x3d55bd0e,0x3d7dbc16,0x3d753c95,0x3d3e3d2c,
0xbc48bd7b,0x3cdbbd67,0x3d62bcf1,0x3d7d3c16,0xbcc43d6d,0xbd5c3d04,0xbd7fbbc9,0xbd3ebd2c,0x3d55bd0e,0x3d803b49,0x3d463d22,0x3c793d78,0xbd800000,0xbd4ebd18,0xbc95bd75,0x3cacbd71,
0xbd0e3d55,0xbd713cac,0xbd75bc95,0xbd18bd4e,0x3d6dbcc4,0x3d783c79,0x3d223d46,0x3b493d80,0xbd7bbc48,0xbd2cbd3e,0xbbc9bd7f,0x3d04bd5c,0x3d353d35,0x3c163d7d,0xbcf13d62,0xbd673cdb,
0xbd35bd35,0x3b49bd80,0x3d46bd22,0x3d7d3c16,0x3d0e3d55,0xbc793d78,0xbd623cf1,0xbd71bcac,0xbcc4bd6d,0x3cdbbd67,0x3d75bc95,0x3d5c3d04,0x3c483d7b,0xbd183d4e,0xbd7f3bc9,0xbd3ebd2c,
0xbd800000,0xbd2cbd3e,0x3bc9bd7f,0x3d4ebd18,0x3d7b3c48,0x3d043d5c,0xbc953d75,0xbd673cdb,0xbd6dbcc4,0xbcacbd71,0x3cf1bd62,0x3d78bc79,0x3d553d0e,0x3c163d7d,0xbd223d46,0xbd803b49,
0x3c48bd7b,0x3d71bcac,0x3d463d22,0xbc163d7d,0x3d353d35,0xbc793d78,0xbd753c95,0xbd3ebd2c,0x3d553d0e,0xbb493d80,0xbd623cf1,0xbd5cbd04,0xbd6d3cc4,0xbd4ebd18,0x3bc9bd7f,0x3d67bcdb,
0x3d0e3d55,0xbcdb3d67,0xbd7f3bc9,0xbd18bd4e,0xbd800000,0xbd04bd5c,0x3cf1bd62,0x3d80bb49,0xbd7b3c48,0xbd2cbd3e,0x3c95bd75,0x3d78bc79,0x3cc4bd6d,0x3d7dbc16,0x3d223d46,0xbcac3d71,
0x3cc43d6d,0xbd3e3d2c,0xbd62bcf1,0x3c16bd7d,0x3d7bbc48,0x3d043d5c,0xbd223d46,0xbd71bcac,0xbd35bd35,0x3cdbbd67,0x3d7f3bc9,0x3c793d78,0xbd553d0e,0xbd4ebd18,0x3c95bd75,0x3d80bb49,
0x3d6d3cc4,0xbb493d80,0xbd753c95,0xbd18bd4e,0x3d0ebd55,0x3d783c79,0x3bc93d7f,0xbd673cdb,0xbd800000,0xbcacbd71,0x3d46bd22,0x3d5c3d04,0xbc483d7b,0xbd7d3c16,0xbcf1bd62,0x3d2cbd3e,
0x3d0ebd55,0x3d673cdb,0xbc953d75,0xbd7dbc16,0x3d6dbcc4,0x3d043d5c,0xbd463d22,0xbd3ebd2c,0x3d7b3c48,0xbb493d80,0xbd7f3bc9,0xbc79bd78,0x3d353d35,0xbd183d4e,0xbd62bcf1,0x3cacbd71,
0x3c483d7b,0xbd713cac,0xbcf1bd62,0x3d4ebd18,0xbcc43d6d,0xbd78bc79,0x3bc9bd7f,0x3d80bb49,0xbd553d0e,0xbd2cbd3e,0x3d22bd46,0x3d5c3d04,0xbd800000,0xbc16bd7d,0x3d75bc95,0x3cdb3d67,
0x3d80,0xbd80bb49,0x3bc9bd7f,0x3d7d3c16,0xbc483d7b,0xbd78bc79,0x3c95bd75,0x3d713cac,0xbcc43d6d,0xbd67bcdb,0x3cf1bd62,0x3d5c3d04,0xbd0e3d55,0xbd4ebd18,0x3d22bd46,0x3d3e3d2c,
0xbd353d35,0xbd2cbd3e,0x3d46bd22,0x3d183d4e,0xbd553d0e,0xbd04bd5c,0x3d62bcf1,0x3cdb3d67,0xbd6d3cc4,0xbcacbd71,0x3d75bc95,0x3c793d78,0xbd7b3c48,0xbc16bd7d,0x3d7fbbc9,0x3b493d80,
0xbd553d0e,0xbcacbd71,0x3d7fbbc9,0xbc163d7d,0x3d80,0xbd78bc79,0x3cf1bd62,0x3d3e3d2c,0xbc48bd7b,0x3d803b49,0xbc953d75,0xbd5cbd04,0xbd6dbcc4,0x3d18bd4e,0x3d223d46,0xbd673cdb,
0x3d7b3c48,0xbcdb3d67,0xbd46bd22,0x3d4ebd18,0x3d35bd35,0x3d043d5c,0xbd753c95,0xbb49bd80,0xbd0e3d55,0xbd2cbd3e,0x3d62bcf1,0x3c793d78,0x3cc43d6d,0xbd7d3c16,0x3bc9bd7f,0x3d713cac,
0x3cc4bd6d,0x3d2c3d3e,0xbd753c95,0x3c16bd7d,0x3d553d0e,0xbd5c3d04,0xbbc9bd7f,0x3d713cac,0x3d80,0xbd67bcdb,0x3d46bd22,0x3c793d78,0xbd7bbc48,0x3d18bd4e,0x3cf13d62,0xbd803b49,
0x3d6dbcc4,0xbb493d80,0xbd62bcf1,0x3d4ebd18,0x3c483d7b,0xbd78bc79,0x3d22bd46,0x3cdb3d67,0xbd353d35,0xbcacbd71,0x3d7f3bc9,0xbd043d5c,0xbd0ebd55,0x3d7dbc16,0xbc953d75,0xbd3ebd2c,
0xbd7b3c48,0x3cdbbd67,0x3cf13d62,0xbd7dbc16,0x3d6d3cc4,0xbd5c3d04,0x3bc9bd7f,0x3d3e3d2c,0xbd0ebd55,0x3d803b49,0xbd223d46,0xbc79bd78,0x3d80,0xbd4ebd18,0x3d75bc95,0xbcac3d71,
0x3d553d0e,0xbd713cac,0x3c95bd75,0x3d183d4e,0xbcc4bd6d,0x3d783c79,0xbd463d22,0xbb49bd80,0xbc483d7b,0xbd2cbd3e,0x3d7fbbc9,0xbd043d5c,0x3d35bd35,0x3c163d7d,0xbd62bcf1,0x3d67bcdb,
0xbd353d35,0x3b49bd80,0x3d223d46,0xbd7dbc16,0x3d55bd0e,0xbc793d78,0xbcf1bd62,0x3d713cac,0xbd6d3cc4,0x3cdbbd67,0x3c953d75,0xbd5cbd04,0x3d7bbc48,0xbd183d4e,0xbbc9bd7f,0x3d3e3d2c,
0x3d80,0xbd2cbd3e,0x3d7f3bc9,0xbd4e3d18,0x3c48bd7b,0x3d043d5c,0xbd75bc95,0x3d67bcdb,0xbcc43d6d,0xbcacbd71,0x3d623cf1,0xbd783c79,0x3d0ebd55,0x3c163d7d,0xbd46bd22,0x3d80bb49,
0xbd7bbc48,0x3d71bcac,0xbd223d46,0x3c16bd7d,0x3d35bd35,0xbc793d78,0xbc95bd75,0x3d3e3d2c,0x3d0ebd55,0xbb493d80,0xbcf1bd62,0x3d5c3d04,0x3cc43d6d,0xbd4ebd18,0x3d7f3bc9,0xbd673cdb,
0x3d55bd0e,0xbcdb3d67,0xbbc9bd7f,0x3d183d4e,0x3d80,0xbd04bd5c,0x3d623cf1,0xbd803b49,0x3c483d7b,0xbd2cbd3e,0x3d753c95,0xbd783c79,0xbd6dbcc4,0x3d7dbc16,0xbd463d22,0x3cacbd71,
0x3d6dbcc4,0xbd3e3d2c,0x3cf1bd62,0xbc163d7d,0xbc48bd7b,0x3d043d5c,0xbd46bd22,0x3d713cac,0xbd353d35,0x3cdbbd67,0xbbc93d7f,0xbc79bd78,0x3d0e3d55,0xbd4ebd18,0x3d753c95,0xbd803b49,
0x3cc4bd6d,0xbb493d80,0xbc95bd75,0x3d183d4e,0xbd55bd0e,0x3d783c79,0xbd7f3bc9,0x3d67bcdb,0x3d80,0xbcacbd71,0x3d223d46,0xbd5cbd04,0x3d7b3c48,0xbd7d3c16,0x3d62bcf1,0xbd2c3d3e,
0xbd55bd0e,0x3d673cdb,0xbd75bc95,0x3d7d3c16,0xbcc4bd6d,0x3d043d5c,0xbd22bd46,0x3d3e3d2c,0x3c48bd7b,0xbb493d80,0xbbc9bd7f,0x3c793d78,0x3d35bd35,0xbd183d4e,0x3cf1bd62,0xbcac3d71,
0x3d7bbc48,0xbd713cac,0x3d62bcf1,0xbd4e3d18,0x3d6d3cc4,0xbd78bc79,0x3d7f3bc9,0xbd803b49,0x3d0e3d55,0xbd2cbd3e,0x3d463d22,0xbd5cbd04,0x3d80,0xbc16bd7d,0x3c953d75,0xbcdbbd67,
0xbd800000,0x3b49bd80,0x3d7f3bc9,0xbc163d7d,0xbd7bbc48,0x3c79bd78,0x3d753c95,0xbcac3d71,0xbd6dbcc4,0x3cdbbd67,0x3d623cf1,0xbd043d5c,0xbd55bd0e,0x3d18bd4e,0x3d463d22,0xbd2c3d3e,
0xbd35bd35,0x3d3ebd2c,0x3d223d46,0xbd4e3d18,0xbd0ebd55,0x3d5cbd04,0x3cf13d62,0xbd673cdb,0xbcc4bd6d,0x3d71bcac,0x3c953d75,0xbd783c79,0xbc48bd7b,0x3d7dbc16,0x3bc93d7f,0xbd803b49,
0xbd0ebd55,0x3d71bcac,0x3bc93d7f,0xbd7dbc16,0xbd800000,0x3c79bd78,0x3d623cf1,0xbd2c3d3e,0x3d7bbc48,0xbb493d80,0xbd75bc95,0x3d04bd5c,0x3cc4bd6d,0x3d4e3d18,0xbd463d22,0xbcdbbd67,
0xbc483d7b,0xbd67bcdb,0x3d22bd46,0x3d183d4e,0x3d353d35,0xbd5c3d04,0xbc95bd75,0x3d80bb49,0xbd55bd0e,0x3d3ebd2c,0x3cf13d62,0xbd783c79,0xbd6d3cc4,0xbc16bd7d,0x3d7f3bc9,0xbcac3d71,
0x3d6d3cc4,0xbd3e3d2c,0xbc95bd75,0x3d7d3c16,0xbd0e3d55,0xbd04bd5c,0x3d7fbbc9,0xbcac3d71,0xbd800000,0x3cdbbd67,0x3d223d46,0xbd783c79,0x3c48bd7b,0x3d4e3d18,0xbd623cf1,0xbb49bd80,
0x3cc43d6d,0xbd80bb49,0x3cf1bd62,0x3d183d4e,0xbd7b3c48,0x3c79bd78,0x3d463d22,0xbd673cdb,0xbd35bd35,0x3d71bcac,0xbbc93d7f,0xbd5cbd04,0x3d55bd0e,0x3c163d7d,0xbd75bc95,0x3d2cbd3e,
0xbc48bd7b,0x3d673cdb,0xbd623cf1,0x3c16bd7d,0xbcc43d6d,0xbd04bd5c,0x3d7f3bc9,0xbd2c3d3e,0x3d55bd0e,0xbb493d80,0xbd46bd22,0x3d78bc79,0xbd800000,0x3d18bd4e,0x3c953d75,0xbd71bcac,
0xbd0e3d55,0xbcacbd71,0x3d753c95,0xbd4e3d18,0x3d6dbcc4,0xbc793d78,0xbd22bd46,0x3d80bb49,0xbd7bbc48,0x3d3ebd2c,0x3bc93d7f,0xbd5cbd04,0x3d353d35,0xbd7d3c16,0x3cf1bd62,0x3cdb3d67,
0xbd35bd35,0x3d803b49,0xbd463d22,0x3c16bd7d,0x3d0e3d55,0xbd78bc79,0x3d62bcf1,0xbcac3d71,0xbcc4bd6d,0x3d673cdb,0xbd753c95,0x3d04bd5c,0x3c483d7b,0xbd4ebd18,0x3d7fbbc9,0xbd2c3d3e,
0xbd800000,0x3d3ebd2c,0xbbc93d7f,0xbd18bd4e,0x3d7b3c48,0xbd5c3d04,0x3c95bd75,0x3cdb3d67,0xbd6dbcc4,0x3d71bcac,0xbcf13d62,0xbc79bd78,0x3d553d0e,0xbd7d3c16,0x3d22bd46,0x3b493d80,
0x3c48bd7b,0x3cac3d71,0xbd46bd22,0x3d7d3c16,0x3d353d35,0xbd78bc79,0x3d75bc95,0xbd2c3d3e,0x3d553d0e,0xbd80bb49,0x3d62bcf1,0xbd043d5c,0xbd6d3cc4,0x3d18bd4e,0xbbc93d7f,0xbcdbbd67,
0x3d0e3d55,0xbd67bcdb,0x3d7fbbc9,0xbd4e3d18,0xbd800000,0x3d5cbd04,0xbcf13d62,0xbb49bd80,0xbd7b3c48,0x3d3ebd2c,0xbc953d75,0xbc79bd78,0x3cc4bd6d,0x3c163d7d,0xbd22bd46,0x3d713cac,
0x3cc43d6d,0xbd2cbd3e,0x3d623cf1,0xbd7dbc16,0x3d7bbc48,0xbd5c3d04,0x3d22bd46,0xbcac3d71,0xbd35bd35,0x3d673cdb,0xbd7fbbc9,0x3d78bc79,0xbd553d0e,0x3d18bd4e,0xbc953d75,0xbb49bd80,
0x3d6d3cc4,0xbd80bb49,0x3d75bc95,0xbd4e3d18,0x3d0ebd55,0xbc793d78,0xbbc9bd7f,0x3cdb3d67,0xbd800000,0x3d71bcac,0xbd463d22,0x3d04bd5c,0xbc483d7b,0xbc16bd7d,0x3cf13d62,0xbd3ebd2c,
0x3d0ebd55,0xbcdb3d67,0x3c95bd75,0xbc163d7d,0x3d6dbcc4,0xbd5c3d04,0x3d46bd22,0xbd2c3d3e,0x3d7b3c48,0xbd80bb49,0x3d7fbbc9,0xbd783c79,0x3d353d35,0xbd4ebd18,0x3d623cf1,0xbd71bcac,
0x3c483d7b,0xbcacbd71,0x3cf13d62,0xbd18bd4e,0xbcc43d6d,0x3c79bd78,0xbbc93d7f,0xbb49bd80,0xbd553d0e,0x3d3ebd2c,0xbd223d46,0x3d04bd5c,0xbd800000,0x3d7dbc16,0xbd753c95,0x3d67bcdb,
0x3d80,0x3b49bd80,0xbbc93d7f,0x3c16bd7d,0xbc483d7b,0x3c79bd78,0xbc953d75,0x3cacbd71,0xbcc43d6d,0x3cdbbd67,0xbcf13d62,0x3d04bd5c,0xbd0e3d55,0x3d18bd4e,0xbd223d46,0x3d2cbd3e,
0xbd353d35,0x3d3ebd2c,0xbd463d22,0x3d4ebd18,0xbd553d0e,0x3d5cbd04,0xbd623cf1,0x3d67bcdb,0xbd6d3cc4,0x3d71bcac,0xbd753c95,0x3d78bc79,0xbd7b3c48,0x3d7dbc16,0xbd7f3bc9,0x3d80bb49,
0xbd553d0e,0x3d71bcac,0xbd7f3bc9,0x3d7d3c16,0x3d80,0x3c79bd78,0xbcf13d62,0x3d2cbd3e,0xbc48bd7b,0xbb493d80,0x3c95bd75,0xbd043d5c,0xbd6dbcc4,0x3d4e3d18,0xbd22bd46,0x3cdb3d67,
0x3d7b3c48,0xbd67bcdb,0x3d463d22,0xbd18bd4e,0x3d35bd35,0xbd5c3d04,0x3d75bc95,0xbd803b49,0xbd0e3d55,0x3d3ebd2c,0xbd623cf1,0x3d78bc79,0x3cc43d6d,0xbc16bd7d,0xbbc93d7f,0x3cacbd71,
0x3cc4bd6d,0xbd3e3d2c,0x3d75bc95,0xbd7dbc16,0x3d553d0e,0xbd04bd5c,0x3bc93d7f,0x3cacbd71,0x3d80,0x3cdbbd67,0xbd463d22,0x3d78bc79,0xbd7bbc48,0x3d4e3d18,0xbcf1bd62,0x3b493d80,
0x3d6dbcc4,0xbd80bb49,0x3d623cf1,0xbd18bd4e,0x3c483d7b,0x3c79bd78,0xbd223d46,0x3d67bcdb,0xbd353d35,0x3d71bcac,0xbd7fbbc9,0x3d5c3d04,0xbd0ebd55,0x3c163d7d,0x3c95bd75,0xbd2c3d3e,
0xbd7b3c48,0x3d673cdb,0xbcf1bd62,0xbc163d7d,0x3d6d3cc4,0xbd04bd5c,0xbbc93d7f,0x3d2cbd3e,0xbd0ebd55,0xbb493d80,0x3d22bd46,0xbd783c79,0x3d80,0x3d18bd4e,0xbd753c95,0x3d713cac,
0x3d553d0e,0xbcacbd71,0xbc953d75,0x3d4ebd18,0xbcc4bd6d,0xbc793d78,0x3d46bd22,0xbd803b49,0xbc483d7b,0x3d3ebd2c,0xbd7f3bc9,0x3d5c3d04,0x3d35bd35,0xbd7d3c16,0x3d623cf1,0xbcdbbd67,
0xbd353d35,0x3d803b49,0xbd22bd46,0xbc163d7d,0x3d55bd0e,0xbd78bc79,0x3cf13d62,0x3cacbd71,0xbd6d3cc4,0x3d673cdb,0xbc95bd75,0xbd043d5c,0x3d7bbc48,0xbd4ebd18,0x3bc93d7f,0x3d2cbd3e,
0x3d80,0x3d3ebd2c,0xbd7fbbc9,0x3d183d4e,0x3c48bd7b,0xbd5c3d04,0x3d753c95,0xbcdbbd67,0xbcc43d6d,0x3d71bcac,0xbd62bcf1,0x3c793d78,0x3d0ebd55,0xbd7d3c16,0x3d463d22,0xbb49bd80,
0xbd7bbc48,0x3cac3d71,0x3d22bd46,0xbd7dbc16,0x3d35bd35,0xbd78bc79,0x3c953d75,0x3d2cbd3e,0x3d0ebd55,0xbd80bb49,0x3cf13d62,0x3d04bd5c,0x3cc43d6d,0x3d18bd4e,0xbd7fbbc9,0x3cdb3d67,
0x3d55bd0e,0xbd67bcdb,0x3bc93d7f,0x3d4ebd18,0x3d80,0x3d5cbd04,0xbd62bcf1,0x3b493d80,0x3c483d7b,0x3d3ebd2c,0xbd75bc95,0x3c793d78,0xbd6dbcc4,0x3c163d7d,0x3d46bd22,0xbd71bcac,
0x3d6dbcc4,0xbd2cbd3e,0xbcf13d62,0x3d7d3c16,0xbc48bd7b,0xbd5c3d04,0x3d463d22,0x3cacbd71,0xbd353d35,0x3d673cdb,0x3bc9bd7f,0xbd783c79,0x3d0e3d55,0x3d18bd4e,0xbd75bc95,0x3b493d80,
0x3cc4bd6d,0xbd80bb49,0x3c953d75,0x3d4ebd18,0xbd55bd0e,0xbc793d78,0x3d7fbbc9,0xbcdbbd67,0x3d80,0x3d71bcac,0xbd22bd46,0xbd043d5c,0x3d7b3c48,0xbc16bd7d,0xbd623cf1,0x3d3e3d2c,
0xbd55bd0e,0xbcdb3d67,0x3d753c95,0x3c16bd7d,0xbcc4bd6d,0xbd5c3d04,0x3d223d46,0x3d2cbd3e,0x3c48bd7b,0xbd80bb49,0x3bc93d7f,0x3d78bc79,0x3d35bd35,0xbd4ebd18,0xbcf13d62,0x3d713cac,
0x3d7bbc48,0xbcacbd71,0xbd623cf1,0x3d183d4e,0x3d6d3cc4,0x3c79bd78,0xbd7fbbc9,0x3b493d80,0x3d0e3d55,0x3d3ebd2c,0xbd46bd22,0xbd043d5c,0x3d80,0x3d7dbc16,0xbc95bd75,0xbd673cdb,
0xbd800000,0x3d803b49,0xbd7fbbc9,0x3d7d3c16,0xbd7bbc48,0x3d783c79,0xbd75bc95,0x3d713cac,0xbd6dbcc4,0x3d673cdb,0xbd62bcf1,0x3d5c3d04,0xbd55bd0e,0x3d4e3d18,0xbd46bd22,0x3d3e3d2c,
0xbd35bd35,0x3d2c3d3e,0xbd22bd46,0x3d183d4e,0xbd0ebd55,0x3d043d5c,0xbcf1bd62,0x3cdb3d67,0xbcc4bd6d,0x3cac3d71,0xbc95bd75,0x3c793d78,0xbc48bd7b,0x3c163d7d,0xbbc9bd7f,0x3b493d80,
0xbd0ebd55,0x3cac3d71,0xbbc9bd7f,0xbc163d7d,0xbd800000,0x3d783c79,0xbd62bcf1,0x3d3e3d2c,0x3d7bbc48,0xbd80bb49,0x3d753c95,0xbd5cbd04,0x3cc4bd6d,0xbd183d4e,0x3d46bd22,0xbd673cdb,
0xbc483d7b,0x3cdbbd67,0xbd223d46,0x3d4ebd18,0x3d353d35,0xbd04bd5c,0x3c953d75,0xbb49bd80,0xbd55bd0e,0x3d2c3d3e,0xbcf1bd62,0x3c793d78,0xbd6d3cc4,0x3d7dbc16,0xbd7fbbc9,0x3d713cac,
0x3d6d3cc4,0xbd2cbd3e,0x3c953d75,0x3c16bd7d,0xbd0e3d55,0x3d5cbd04,0xbd7f3bc9,0x3d713cac,0xbd800000,0x3d673cdb,0xbd22bd46,0x3c793d78,0x3c48bd7b,0xbd183d4e,0x3d62bcf1,0xbd803b49,
0x3cc43d6d,0x3b49bd80,0xbcf13d62,0x3d4ebd18,0xbd7b3c48,0x3d783c79,0xbd46bd22,0x3cdb3d67,0xbd35bd35,0x3cac3d71,0x3bc9bd7f,0xbd043d5c,0x3d55bd0e,0xbd7d3c16,0x3d753c95,0xbd3ebd2c,
0xbc48bd7b,0xbcdb3d67,0x3d62bcf1,0xbd7dbc16,0xbcc43d6d,0x3d5cbd04,0xbd7fbbc9,0x3d3e3d2c,0x3d55bd0e,0xbd80bb49,0x3d463d22,0xbc79bd78,0xbd800000,0x3d4e3d18,0xbc95bd75,0xbcac3d71,
0xbd0e3d55,0x3d71bcac,0xbd75bc95,0x3d183d4e,0x3d6dbcc4,0xbd78bc79,0x3d223d46,0xbb49bd80,0xbd7bbc48,0x3d2c3d3e,0xbbc9bd7f,0xbd043d5c,0x3d353d35,0xbc16bd7d,0xbcf13d62,0x3d67bcdb,
0xbd35bd35,0xbb493d80,0x3d46bd22,0xbd7dbc16,0x3d0e3d55,0x3c79bd78,0xbd623cf1,0x3d713cac,0xbcc4bd6d,0xbcdb3d67,0x3d75bc95,0xbd5cbd04,0x3c483d7b,0x3d18bd4e,0xbd7f3bc9,0x3d3e3d2c,
0xbd800000,0x3d2c3d3e,0x3bc9bd7f,0xbd4e3d18,0x3d7b3c48,0xbd04bd5c,0xbc953d75,0x3d67bcdb,0xbd6dbcc4,0x3cac3d71,0x3cf1bd62,0xbd783c79,0x3d553d0e,0xbc16bd7d,0xbd223d46,0x3d80bb49,
0x3c48bd7b,0xbd713cac,0x3d463d22,0x3c16bd7d,0x3d353d35,0x3c79bd78,0xbd753c95,0x3d3e3d2c,0x3d553d0e,0x3b49bd80,0xbd623cf1,0x3d5c3d04,0xbd6d3cc4,0x3d4e3d18,0x3bc9bd7f,0xbd673cdb,
0x3d0e3d55,0x3cdbbd67,0xbd7f3bc9,0x3d183d4e,0xbd800000,0x3d043d5c,0x3cf1bd62,0xbd803b49,0xbd7b3c48,0x3d2c3d3e,0x3c95bd75,0xbd783c79,0x3cc4bd6d,0xbd7d3c16,0x3d223d46,0x3cacbd71,
0x3cc43d6d,0x3d3ebd2c,0xbd62bcf1,0xbc163d7d,0x3d7bbc48,0xbd04bd5c,0xbd223d46,0x3d713cac,0xbd35bd35,0xbcdb3d67,0x3d7f3bc9,0xbc79bd78,0xbd553d0e,0x3d4e3d18,0x3c95bd75,0xbd803b49,
0x3d6d3cc4,0x3b49bd80,0xbd753c95,0x3d183d4e,0x3d0ebd55,0xbd78bc79,0x3bc93d7f,0x3d67bcdb,0xbd800000,0x3cac3d71,0x3d46bd22,0xbd5cbd04,0xbc483d7b,0x3d7dbc16,0xbcf1bd62,0xbd2c3d3e,
0x3d0ebd55,0xbd67bcdb,0xbc953d75,0x3d7d3c16,0x3d6dbcc4,0xbd04bd5c,0xbd463d22,0x3d3e3d2c,0x3d7b3c48,0x3b49bd80,0xbd7f3bc9,0x3c793d78,0x3d353d35,0x3d18bd4e,0xbd62bcf1,0xbcac3d71,
0x3c483d7b,0x3d71bcac,0xbcf1bd62,0xbd4e3d18,0xbcc43d6d,0x3d783c79,0x3bc9bd7f,0xbd803b49,0xbd553d0e,0x3d2c3d3e,0x3d22bd46,0xbd5cbd04,0xbd800000,0x3c163d7d,0x3d75bc95,0xbcdbbd67,
0x3d80,0x3d803b49,0x3bc9bd7f,0xbd7dbc16,0xbc483d7b,0x3d783c79,0x3c95bd75,0xbd71bcac,0xbcc43d6d,0x3d673cdb,0x3cf1bd62,0xbd5cbd04,0xbd0e3d55,0x3d4e3d18,0x3d22bd46,0xbd3ebd2c,
0xbd353d35,0x3d2c3d3e,0x3d46bd22,0xbd18bd4e,0xbd553d0e,0x3d043d5c,0x3d62bcf1,0xbcdbbd67,0xbd6d3cc4,0x3cac3d71,0x3d75bc95,0xbc79bd78,0xbd7b3c48,0x3c163d7d,0x3d7fbbc9,0xbb49bd80,
0xbd553d0e,0x3cac3d71,0x3d7fbbc9,0x3c16bd7d,0x3d80,0x3d783c79,0x3cf1bd62,0xbd3ebd2c,0xbc48bd7b,0xbd80bb49,0xbc953d75,0x3d5c3d04,0xbd6dbcc4,0xbd183d4e,0x3d223d46,0x3d67bcdb,
0x3d7b3c48,0x3cdbbd67,0xbd46bd22,0xbd4e3d18,0x3d35bd35,0xbd04bd5c,0xbd753c95,0x3b493d80,0xbd0e3d55,0x3d2c3d3e,0x3d62bcf1,0xbc79bd78,0x3cc43d6d,0x3d7dbc16,0x3bc9bd7f,0xbd71bcac,
0x3cc4bd6d,0xbd2cbd3e,0xbd753c95,0xbc163d7d,0x3d553d0e,0x3d5cbd04,0xbbc9bd7f,0xbd71bcac,0x3d80,0x3d673cdb,0x3d46bd22,0xbc79bd78,0xbd7bbc48,0xbd183d4e,0x3cf13d62,0x3d80bb49,
0x3d6dbcc4,0x3b49bd80,0xbd62bcf1,0xbd4e3d18,0x3c483d7b,0x3d783c79,0x3d22bd46,0xbcdbbd67,0xbd353d35,0x3cac3d71,0x3d7f3bc9,0x3d04bd5c,0xbd0ebd55,0xbd7d3c16,0xbc953d75,0x3d3e3d2c,
0xbd7b3c48,0xbcdb3d67,0x3cf13d62,0x3d7d3c16,0x3d6d3cc4,0x3d5cbd04,0x3bc9bd7f,0xbd3ebd2c,0xbd0ebd55,0xbd80bb49,0xbd223d46,0x3c793d78,0x3d80,0x3d4e3d18,0x3d75bc95,0x3cacbd71,
0x3d553d0e,0x3d71bcac,0x3c95bd75,0xbd18bd4e,0xbcc4bd6d,0xbd78bc79,0xbd463d22,0x3b493d80,0xbc483d7b,0x3d2c3d3e,0x3d7fbbc9,0x3d04bd5c,0x3d35bd35,0xbc16bd7d,0xbd62bcf1,0xbd673cdb,
0xbd353d35,0xbb493d80,0x3d223d46,0x3d7d3c16,0x3d55bd0e,0x3c79bd78,0xbcf1bd62,0xbd71bcac,0xbd6d3cc4,0xbcdb3d67,0x3c953d75,0x3d5c3d04,0x3d7bbc48,0x3d18bd4e,0xbbc9bd7f,0xbd3ebd2c,
0x3d80,0x3d2c3d3e,0x3d7f3bc9,0x3d4ebd18,0x3c48bd7b,0xbd04bd5c,0xbd75bc95,0xbd673cdb,0xbcc43d6d,0x3cac3d71,0x3d623cf1,0x3d78bc79,0x3d0ebd55,0xbc16bd7d,0xbd46bd22,0xbd803b49,
0xbd7bbc48,0xbd713cac,0xbd223d46,0xbc163d7d,0x3d35bd35,0x3c79bd78,0xbc95bd75,0xbd3ebd2c,0x3d0ebd55,0x3b49bd80,0xbcf1bd62,0xbd5cbd04,0x3cc43d6d,0x3d4e3d18,0x3d7f3bc9,0x3d67bcdb,
0x3d55bd0e,0x3cdbbd67,0xbbc9bd7f,0xbd18bd4e,0x3d80,0x3d043d5c,0x3d623cf1,0x3d80bb49,0x3c483d7b,0x3d2c3d3e,0x3d753c95,0x3d78bc79,0xbd6dbcc4,0xbd7d3c16,0xbd463d22,0xbcac3d71,
0x3d6dbcc4,0x3d3ebd2c,0x3cf1bd62,0x3c16bd7d,0xbc48bd7b,0xbd04bd5c,0xbd46bd22,0xbd71bcac,0xbd353d35,0xbcdb3d67,0xbbc93d7f,0x3c793d78,0x3d0e3d55,0x3d4e3d18,0x3d753c95,0x3d80bb49,
0x3cc4bd6d,0x3b49bd80,0xbc95bd75,0xbd18bd4e,0xbd55bd0e,0xbd78bc79,0xbd7f3bc9,0xbd673cdb,0x3d80,0x3cac3d71,0x3d223d46,0x3d5c3d04,0x3d7b3c48,0x3d7dbc16,0x3d62bcf1,0x3d2cbd3e,
0xbd55bd0e,0xbd67bcdb,0xbd75bc95,0xbd7dbc16,0xbcc4bd6d,0xbd04bd5c,0xbd22bd46,0xbd3ebd2c,0x3c48bd7b,0x3b49bd80,0xbbc9bd7f,0xbc79bd78,0x3d35bd35,0x3d18bd4e,0x3cf1bd62,0x3cacbd71,
0x3d7bbc48,0x3d71bcac,0x3d62bcf1,0x3d4ebd18,0x3d6d3cc4,0x3d783c79,0x3d7f3bc9,0x3d80bb49,0x3d0e3d55,0x3d2c3d3e,0x3d463d22,0x3d5c3d04,0x3d80,0x3c163d7d,0x3c953d75,0x3cdb3d67,
0xbd800000,0xbb493d80,0x3d7f3bc9,0x3c16bd7d,0xbd7bbc48,0xbc793d78,0x3d753c95,0x3cacbd71,0xbd6dbcc4,0xbcdb3d67,0x3d623cf1,0x3d04bd5c,0xbd55bd0e,0xbd183d4e,0x3d463d22,0x3d2cbd3e,
0xbd35bd35,0xbd3e3d2c,0x3d223d46,0x3d4ebd18,0xbd0ebd55,0xbd5c3d04,0x3cf13d62,0x3d67bcdb,0xbcc4bd6d,0xbd713cac,0x3c953d75,0x3d78bc79,0xbc48bd7b,0xbd7d3c16,0x3bc93d7f,0x3d80bb49,
0xbd0ebd55,0xbd713cac,0x3bc93d7f,0x3d7d3c16,0xbd800000,0xbc793d78,0x3d623cf1,0x3d2cbd3e,0x3d7bbc48,0x3b49bd80,0xbd75bc95,0xbd043d5c,0x3cc4bd6d,0xbd4ebd18,0xbd463d22,0x3cdb3d67,
0xbc483d7b,0x3d673cdb,0x3d22bd46,0xbd18bd4e,0x3d353d35,0x3d5cbd04,0xbc95bd75,0xbd803b49,0xbd55bd0e,0xbd3e3d2c,0x3cf13d62,0x3d78bc79,0xbd6d3cc4,0x3c163d7d,0x3d7f3bc9,0x3cacbd71,
0x3d6d3cc4,0x3d3ebd2c,0xbc95bd75,0xbd7dbc16,0xbd0e3d55,0x3d043d5c,0x3d7fbbc9,0x3cacbd71,0xbd800000,0xbcdb3d67,0x3d223d46,0x3d78bc79,0x3c48bd7b,0xbd4ebd18,0xbd623cf1,0x3b493d80,
0x3cc43d6d,0x3d803b49,0x3cf1bd62,0xbd18bd4e,0xbd7b3c48,0xbc793d78,0x3d463d22,0x3d67bcdb,0xbd35bd35,0xbd713cac,0xbbc93d7f,0x3d5c3d04,0x3d55bd0e,0xbc16bd7d,0xbd75bc95,0xbd2c3d3e,
0xbc48bd7b,0xbd67bcdb,0xbd623cf1,0xbc163d7d,0xbcc43d6d,0x3d043d5c,0x3d7f3bc9,0x3d2cbd3e,0x3d55bd0e,0x3b49bd80,0xbd46bd22,0xbd783c79,0xbd800000,0xbd183d4e,0x3c953d75,0x3d713cac,
0xbd0e3d55,0x3cac3d71,0x3d753c95,0x3d4ebd18,0x3d6dbcc4,0x3c79bd78,0xbd22bd46,0xbd803b49,0xbd7bbc48,0xbd3e3d2c,0x3bc93d7f,0x3d5c3d04,0x3d353d35,0x3d7dbc16,0x3cf1bd62,0xbcdbbd67,
0xbd35bd35,0xbd80bb49,0xbd463d22,0xbc163d7d,0x3d0e3d55,0x3d783c79,0x3d62bcf1,0x3cacbd71,0xbcc4bd6d,0xbd67bcdb,0xbd753c95,0xbd043d5c,0x3c483d7b,0x3d4e3d18,0x3d7fbbc9,0x3d2cbd3e,
0xbd800000,0xbd3e3d2c,0xbbc93d7f,0x3d183d4e,0x3d7b3c48,0x3d5cbd04,0x3c95bd75,0xbcdbbd67,0xbd6dbcc4,0xbd713cac,0xbcf13d62,0x3c793d78,0x3d553d0e,0x3d7dbc16,0x3d22bd46,0xbb49bd80,
0x3c48bd7b,0xbcacbd71,0xbd46bd22,0xbd7dbc16,0x3d353d35,0x3d783c79,0x3d75bc95,0x3d2cbd3e,0x3d553d0e,0x3d803b49,0x3d62bcf1,0x3d04bd5c,0xbd6d3cc4,0xbd183d4e,0xbbc93d7f,0x3cdb3d67,
0x3d0e3d55,0x3d673cdb,0x3d7fbbc9,0x3d4ebd18,0xbd800000,0xbd5c3d04,0xbcf13d62,0x3b493d80,0xbd7b3c48,0xbd3e3d2c,0xbc953d75,0x3c793d78,0x3cc4bd6d,0xbc16bd7d,0xbd22bd46,0xbd71bcac,
0x3cc43d6d,0x3d2c3d3e,0x3d623cf1,0x3d7d3c16,0x3d7bbc48,0x3d5cbd04,0x3d22bd46,0x3cacbd71,0xbd35bd35,0xbd67bcdb,0xbd7fbbc9,0xbd783c79,0xbd553d0e,0xbd183d4e,0xbc953d75,0x3b493d80,
0x3d6d3cc4,0x3d803b49,0x3d75bc95,0x3d4ebd18,0x3d0ebd55,0x3c79bd78,0xbbc9bd7f,0xbcdbbd67,0xbd800000,0xbd713cac,0xbd463d22,0xbd043d5c,0xbc483d7b,0x3c163d7d,0x3cf13d62,0x3d3e3d2c,
0x3d0ebd55,0x3cdbbd67,0x3c95bd75,0x3c16bd7d,0x3d6dbcc4,0x3d5cbd04,0x3d46bd22,0x3d2cbd3e,0x3d7b3c48,0x3d803b49,0x3d7fbbc9,0x3d78bc79,0x3d353d35,0x3d4e3d18,0x3d623cf1,0x3d713cac,
0x3c483d7b,0x3cac3d71,0x3cf13d62,0x3d183d4e,0xbcc43d6d,0xbc793d78,0xbbc93d7f,0x3b493d80,0xbd553d0e,0xbd3e3d2c,0xbd223d46,0xbd043d5c,0xbd800000,0xbd7d3c16,0xbd753c95,0xbd673cdb,
0x3d80,0xbbc93d7f,0xbc483d7b,0xbc953d75,0xbcc43d6d,0xbcf13d62,0xbd0e3d55,0xbd223d46,0xbd353d35,0xbd463d22,0xbd553d0e,0xbd623cf1,0xbd6d3cc4,0xbd753c95,0xbd7b3c48,0xbd7f3bc9,
0xbd800000,0xbd7fbbc9,0xbd7bbc48,0xbd75bc95,0xbd6dbcc4,0xbd62bcf1,0xbd55bd0e,0xbd46bd22,0xbd35bd35,0xbd22bd46,0xbd0ebd55,0xbcf1bd62,0xbcc4bd6d,0xbc95bd75,0xbc48bd7b,0xbbc9bd7f,
0xbd6d3cc4,0xbd7f3bc9,0xbd7bbc48,0xbd62bcf1,0x3d80,0xbc953d75,0xbd0e3d55,0xbd463d22,0x3cc4bd6d,0x3d22bd46,0x3d55bd0e,0x3d75bc95,0xbd35bd35,0xbcf1bd62,0xbc48bd7b,0x3bc9bd7f,
0x3cc43d6d,0x3bc93d7f,0xbc483d7b,0xbcf13d62,0x3d800000,0x3d753c95,0x3d553d0e,0x3d223d46,0xbd6dbcc4,0xbd46bd22,0xbd0ebd55,0xbc95bd75,0xbd353d35,0xbd623cf1,0xbd7b3c48,0xbd7fbbc9,
0x3d35bd35,0x3d75bc95,0x3d7b3c48,0x3d463d22,0x3cc43d6d,0xbbc93d7f,0xbd0e3d55,0xbd623cf1,0x3d80,0xbcf13d62,0xbd553d0e,0xbd7f3bc9,0xbd6dbcc4,0xbd22bd46,0xbc48bd7b,0x3c95bd75,
0x3d353d35,0x3c953d75,0xbc483d7b,0xbd223d46,0xbd6d3cc4,0xbd7fbbc9,0xbd55bd0e,0xbcf1bd62,0xbd800000,0xbd62bcf1,0xbd0ebd55,0xbbc9bd7f,0x3cc4bd6d,0x3d46bd22,0x3d7bbc48,0x3d753c95,
0xbd6dbcc4,0xbcf1bd62,0x3c48bd7b,0x3d46bd22,0x3d353d35,0x3bc93d7f,0xbd0e3d55,0xbd753c95,0xbcc4bd6d,0x3c95bd75,0x3d55bd0e,0x3d7f3bc9,0x3d80,0xbd223d46,0xbd7b3c48,0xbd62bcf1,
0xbcc43d6d,0xbd623cf1,0xbd7bbc48,0xbd22bd46,0x3d35bd35,0x3d7fbbc9,0x3d553d0e,0x3c953d75,0xbd6d3cc4,0xbd75bc95,0xbd0ebd55,0x3bc9bd7f,0x3d800000,0x3d463d22,0x3c483d7b,0xbcf13d62,
0xbd800000,0xbd22bd46,0x3c48bd7b,0x3d62bcf1,0x3d6d3cc4,0x3c953d75,0xbd0e3d55,0xbd7f3bc9,0xbd35bd35,0x3bc9bd7f,0x3d55bd0e,0x3d753c95,0x3cc43d6d,0xbcf13d62,0xbd7b3c48,0xbd46bd22,
0x3d80,0xbd463d22,0xbd7bbc48,0xbcf1bd62,0x3cc4bd6d,0x3d75bc95,0x3d553d0e,0x3bc93d7f,0xbd353d35,0xbd7fbbc9,0xbd0ebd55,0x3c95bd75,0x3d6dbcc4,0x3d623cf1,0x3c483d7b,0xbd223d46,
0xbcc4bd6d,0x3d22bd46,0x3d7b3c48,0x3c953d75,0x3d800000,0x3cf13d62,0xbd0e3d55,0xbd7fbbc9,0x3d6d3cc4,0x3bc93d7f,0xbd553d0e,0xbd62bcf1,0xbd353d35,0xbd75bc95,0xbc48bd7b,0x3d46bd22,
0x3d6dbcc4,0x3d463d22,0xbc483d7b,0xbd753c95,0x3d80,0xbd623cf1,0xbd55bd0e,0x3bc9bd7f,0xbcc43d6d,0xbd7f3bc9,0xbd0ebd55,0x3cf1bd62,0xbd35bd35,0x3c95bd75,0x3d7bbc48,0x3d223d46,
0x3d353d35,0xbcf13d62,0xbd7bbc48,0xbbc9bd7f,0x3d6dbcc4,0x3d223d46,0xbd0e3d55,0xbd75bc95,0xbd800000,0xbc95bd75,0x3d55bd0e,0x3d463d22,0xbcc43d6d,0xbd7fbbc9,0xbc48bd7b,0x3d62bcf1,
0x3d35bd35,0x3d623cf1,0xbc483d7b,0xbd7f3bc9,0xbcc4bd6d,0x3d46bd22,0x3d553d0e,0xbc953d75,0x3d80,0xbd753c95,0xbd0ebd55,0x3d22bd46,0x3d6d3cc4,0xbbc93d7f,0xbd7b3c48,0xbcf1bd62,
0x3cc4bd6d,0x3d753c95,0xbc483d7b,0xbd7fbbc9,0x3d35bd35,0x3d463d22,0xbd0e3d55,0xbd62bcf1,0x3d6dbcc4,0x3cf13d62,0xbd553d0e,0xbd22bd46,0x3d800000,0x3bc93d7f,0xbd7b3c48,0xbc95bd75,
0x3d6d3cc4,0xbc953d75,0xbd7bbc48,0x3bc9bd7f,0x3d353d35,0xbd223d46,0xbd55bd0e,0x3cf1bd62,0x3cc43d6d,0xbd623cf1,0xbd0ebd55,0x3d46bd22,0x3d80,0xbd7f3bc9,0xbc48bd7b,0x3d75bc95,
0xbd800000,0xbd7fbbc9,0xbd7bbc48,0xbd75bc95,0xbd6dbcc4,0xbd62bcf1,0xbd55bd0e,0xbd46bd22,0xbd35bd35,0xbd22bd46,0xbd0ebd55,0xbcf1bd62,0xbcc4bd6d,0xbc95bd75,0xbc48bd7b,0xbbc9bd7f,
0x8000bd80,0x3bc9bd7f,0x3c48bd7b,0x3c95bd75,0x3cc4bd6d,0x3cf1bd62,0x3d0ebd55,0x3d22bd46,0x3d35bd35,0x3d46bd22,0x3d55bd0e,0x3d62bcf1,0x3d6dbcc4,0x3d75bc95,0x3d7bbc48,0x3d7fbbc9,
0xbcc4bd6d,0xbbc9bd7f,0x3c48bd7b,0x3cf1bd62,0xbd800000,0xbd75bc95,0xbd55bd0e,0xbd22bd46,0x3d6d3cc4,0x3d463d22,0x3d0e3d55,0x3c953d75,0x3d35bd35,0x3d62bcf1,0x3d7bbc48,0x3d7f3bc9,
0xbd6d3cc4,0xbd7f3bc9,0xbd7bbc48,0xbd62bcf1,0x80003d80,0xbc953d75,0xbd0e3d55,0xbd463d22,0x3cc4bd6d,0x3d22bd46,0x3d55bd0e,0x3d75bc95,0xbd35bd35,0xbcf1bd62,0xbc48bd7b,0x3bc9bd7f,
0x3d353d35,0x3c953d75,0xbc483d7b,0xbd223d46,0xbd6d3cc4,0xbd7fbbc9,0xbd55bd0e,0xbcf1bd62,0xbd800000,0xbd62bcf1,0xbd0ebd55,0xbbc9bd7f,0x3cc4bd6d,0x3d46bd22,0x3d7bbc48,0x3d753c95,
0xbd353d35,0xbd753c95,0xbd7bbc48,0xbd46bd22,0xbcc4bd6d,0x3bc9bd7f,0x3d0ebd55,0x3d62bcf1,0x8000bd80,0x3cf1bd62,0x3d55bd0e,0x3d7fbbc9,0x3d6d3cc4,0x3d223d46,0x3c483d7b,0xbc953d75,
0x3cc4bd6d,0x3d62bcf1,0x3d7b3c48,0x3d223d46,0xbd353d35,0xbd7f3bc9,0xbd55bd0e,0xbc95bd75,0x3d6dbcc4,0x3d753c95,0x3d0e3d55,0xbbc93d7f,0xbd800000,0xbd46bd22,0xbc48bd7b,0x3cf1bd62,
0xbd6dbcc4,0xbcf1bd62,0x3c48bd7b,0x3d46bd22,0x3d353d35,0x3bc93d7f,0xbd0e3d55,0xbd753c95,0xbcc4bd6d,0x3c95bd75,0x3d55bd0e,0x3d7f3bc9,0x80003d80,0xbd223d46,0xbd7b3c48,0xbd62bcf1,
0x8000bd80,0x3d46bd22,0x3d7b3c48,0x3cf13d62,0xbcc43d6d,0xbd753c95,0xbd55bd0e,0xbbc9bd7f,0x3d35bd35,0x3d7f3bc9,0x3d0e3d55,0xbc953d75,0xbd6d3cc4,0xbd62bcf1,0xbc48bd7b,0x3d22bd46,
0xbd800000,0xbd22bd46,0x3c48bd7b,0x3d62bcf1,0x3d6d3cc4,0x3c953d75,0xbd0e3d55,0xbd7f3bc9,0xbd35bd35,0x3bc9bd7f,0x3d55bd0e,0x3d753c95,0x3cc43d6d,0xbcf13d62,0xbd7b3c48,0xbd46bd22,
0x3d6dbcc4,0x3d463d22,0xbc483d7b,0xbd753c95,0x80003d80,0xbd623cf1,0xbd55bd0e,0x3bc9bd7f,0xbcc43d6d,0xbd7f3bc9,0xbd0ebd55,0x3cf1bd62,0xbd35bd35,0x3c95bd75,0x3d7bbc48,0x3d223d46,
0x3cc43d6d,0xbd223d46,0xbd7bbc48,0xbc95bd75,0xbd800000,0xbcf1bd62,0x3d0ebd55,0x3d7f3bc9,0xbd6dbcc4,0xbbc9bd7f,0x3d55bd0e,0x3d623cf1,0x3d35bd35,0x3d753c95,0x3c483d7b,0xbd463d22,
0xbd353d35,0xbd62bcf1,0x3c48bd7b,0x3d7fbbc9,0x3cc43d6d,0xbd463d22,0xbd55bd0e,0x3c95bd75,0x8000bd80,0x3d75bc95,0x3d0e3d55,0xbd223d46,0xbd6dbcc4,0x3bc9bd7f,0x3d7bbc48,0x3cf13d62,
0x3d353d35,0xbcf13d62,0xbd7bbc48,0xbbc9bd7f,0x3d6dbcc4,0x3d223d46,0xbd0e3d55,0xbd75bc95,0xbd800000,0xbc95bd75,0x3d55bd0e,0x3d463d22,0xbcc43d6d,0xbd7fbbc9,0xbc48bd7b,0x3d62bcf1,
0x3d6d3cc4,0xbc953d75,0xbd7bbc48,0x3bc9bd7f,0x3d353d35,0xbd223d46,0xbd55bd0e,0x3cf1bd62,0x3cc43d6d,0xbd623cf1,0xbd0ebd55,0x3d46bd22,0x80003d80,0xbd7f3bc9,0xbc48bd7b,0x3d75bc95,
0xbcc43d6d,0xbd75bc95,0x3c48bd7b,0x3d7f3bc9,0xbd353d35,0xbd46bd22,0x3d0ebd55,0x3d623cf1,0xbd6d3cc4,0xbcf1bd62,0x3d55bd0e,0x3d223d46,0xbd800000,0xbbc9bd7f,0x3d7bbc48,0x3c953d75,
0x3d80,0xbd7fbbc9,0x3c48bd7b,0x3d753c95,0xbcc43d6d,0xbd62bcf1,0x3d0ebd55,0x3d463d22,0xbd353d35,0xbd22bd46,0x3d55bd0e,0x3cf13d62,0xbd6d3cc4,0xbc95bd75,0x3d7bbc48,0x3bc93d7f,
0xbd800000,0x3bc9bd7f,0x3d7b3c48,0xbc953d75,0xbd6dbcc4,0x3cf1bd62,0x3d553d0e,0xbd223d46,0xbd35bd35,0x3d46bd22,0x3d0e3d55,0xbd623cf1,0xbcc4bd6d,0x3d75bc95,0x3c483d7b,0xbd7f3bc9,
0xbd6d3cc4,0xbbc9bd7f,0x3d7b3c48,0xbcf13d62,0x3d80,0xbd75bc95,0x3d0ebd55,0x3d223d46,0x3cc4bd6d,0x3d463d22,0xbd553d0e,0xbc95bd75,0xbd35bd35,0x3d62bcf1,0x3c483d7b,0xbd7fbbc9,
0x3cc43d6d,0xbd7f3bc9,0x3c48bd7b,0x3d623cf1,0x3d800000,0xbc953d75,0xbd55bd0e,0x3d46bd22,0xbd6dbcc4,0x3d22bd46,0x3d0e3d55,0xbd753c95,0xbd353d35,0xbcf1bd62,0x3d7bbc48,0xbbc93d7f,
0x3d35bd35,0x3c953d75,0xbd7bbc48,0x3d22bd46,0x3cc43d6d,0xbd7fbbc9,0x3d0ebd55,0x3cf13d62,0x3d80,0xbd62bcf1,0x3d55bd0e,0x3bc93d7f,0xbd6dbcc4,0x3d46bd22,0x3c483d7b,0xbd75bc95,
0x3d353d35,0xbd753c95,0x3c48bd7b,0x3d463d22,0xbd6d3cc4,0x3bc9bd7f,0x3d553d0e,0xbd623cf1,0xbd800000,0x3cf1bd62,0x3d0e3d55,0xbd7f3bc9,0x3cc4bd6d,0x3d223d46,0xbd7b3c48,0x3c95bd75,
0xbd6dbcc4,0x3d62bcf1,0xbc483d7b,0xbd22bd46,0x3d353d35,0xbd7f3bc9,0x3d0ebd55,0x3c953d75,0xbcc4bd6d,0x3d753c95,0xbd553d0e,0x3bc9bd7f,0x3d80,0xbd46bd22,0x3d7bbc48,0xbcf13d62,
0xbcc43d6d,0xbcf1bd62,0x3d7b3c48,0xbd463d22,0x3d35bd35,0x3bc93d7f,0xbd55bd0e,0x3d75bc95,0xbd6d3cc4,0x3c95bd75,0x3d0e3d55,0xbd7fbbc9,0x3d800000,0xbd223d46,0xbc48bd7b,0x3d623cf1,
0xbd800000,0x3d46bd22,0xbc483d7b,0xbcf1bd62,0x3d6d3cc4,0xbd753c95,0x3d0ebd55,0x3bc93d7f,0xbd35bd35,0x3d7f3bc9,0xbd553d0e,0x3c95bd75,0x3cc43d6d,0xbd62bcf1,0x3d7bbc48,0xbd223d46,
0x3d80,0xbd22bd46,0x3d7b3c48,0xbd623cf1,0x3cc4bd6d,0x3c953d75,0xbd55bd0e,0x3d7fbbc9,0xbd353d35,0x3bc9bd7f,0x3d0e3d55,0xbd75bc95,0x3d6dbcc4,0xbcf13d62,0xbc48bd7b,0x3d463d22,
0xbcc4bd6d,0x3d463d22,0xbd7bbc48,0x3d75bc95,0x3d800000,0xbd623cf1,0x3d0ebd55,0xbbc93d7f,0x3d6d3cc4,0xbd7f3bc9,0x3d55bd0e,0xbcf13d62,0xbd353d35,0x3c95bd75,0x3c483d7b,0xbd22bd46,
0x3d6dbcc4,0xbd223d46,0x3c48bd7b,0x3c953d75,0x3d80,0xbcf1bd62,0x3d553d0e,0xbd7fbbc9,0xbcc43d6d,0xbbc9bd7f,0x3d0e3d55,0xbd62bcf1,0xbd35bd35,0x3d753c95,0xbd7b3c48,0x3d46bd22,
0x3d353d35,0xbd62bcf1,0x3d7b3c48,0xbd7f3bc9,0x3d6dbcc4,0xbd463d22,0x3d0ebd55,0xbc953d75,0xbd800000,0x3d75bc95,0xbd553d0e,0x3d22bd46,0xbcc43d6d,0x3bc9bd7f,0x3c483d7b,0xbcf1bd62,
0x3d35bd35,0xbcf13d62,0x3c48bd7b,0x3bc93d7f,0xbcc4bd6d,0x3d223d46,0xbd55bd0e,0x3d753c95,0x3d80,0xbc95bd75,0x3d0e3d55,0xbd46bd22,0x3d6d3cc4,0xbd7fbbc9,0x3d7bbc48,0xbd623cf1,
0x3cc4bd6d,0xbc953d75,0x3c48bd7b,0xbbc93d7f,0x3d35bd35,0xbd223d46,0x3d0ebd55,0xbcf13d62,0x3d6dbcc4,0xbd623cf1,0x3d55bd0e,0xbd463d22,0x3d800000,0xbd7f3bc9,0x3d7bbc48,0xbd753c95,
0x3d6d3cc4,0xbd75bc95,0x3d7b3c48,0xbd7fbbc9,0x3d353d35,0xbd46bd22,0x3d553d0e,0xbd62bcf1,0x3cc43d6d,0xbcf1bd62,0x3d0e3d55,0xbd22bd46,0x3d80,0xbbc9bd7f,0x3c483d7b,0xbc95bd75,
0xbd800000,0x3bc9bd7f,0x3d7b3c48,0xbc953d75,0xbd6dbcc4,0x3cf1bd62,0x3d553d0e,0xbd223d46,0xbd35bd35,0x3d46bd22,0x3d0e3d55,0xbd623cf1,0xbcc4bd6d,0x3d75bc95,0x3c483d7b,0xbd7f3bc9,
0x8000bd80,0x3d7f3bc9,0xbc483d7b,0xbd75bc95,0x3cc4bd6d,0x3d623cf1,0xbd0e3d55,0xbd46bd22,0x3d35bd35,0x3d223d46,0xbd553d0e,0xbcf1bd62,0x3d6dbcc4,0x3c953d75,0xbd7b3c48,0xbbc9bd7f,
0xbcc4bd6d,0x3d7fbbc9,0xbc483d7b,0xbd62bcf1,0xbd800000,0x3c95bd75,0x3d553d0e,0xbd463d22,0x3d6d3cc4,0xbd223d46,0xbd0ebd55,0x3d75bc95,0x3d35bd35,0x3cf13d62,0xbd7b3c48,0x3bc9bd7f,
0xbd6d3cc4,0xbbc9bd7f,0x3d7b3c48,0xbcf13d62,0x80003d80,0xbd75bc95,0x3d0ebd55,0x3d223d46,0x3cc4bd6d,0x3d463d22,0xbd553d0e,0xbc95bd75,0xbd35bd35,0x3d62bcf1,0x3c483d7b,0xbd7fbbc9,
0x3d353d35,0xbd753c95,0x3c48bd7b,0x3d463d22,0xbd6d3cc4,0x3bc9bd7f,0x3d553d0e,0xbd623cf1,0xbd800000,0x3cf1bd62,0x3d0e3d55,0xbd7f3bc9,0x3cc4bd6d,0x3d223d46,0xbd7b3c48,0x3c95bd75,
0xbd353d35,0xbc95bd75,0x3d7b3c48,0xbd223d46,0xbcc4bd6d,0x3d7f3bc9,0xbd0e3d55,0xbcf1bd62,0x8000bd80,0x3d623cf1,0xbd553d0e,0xbbc9bd7f,0x3d6d3cc4,0xbd463d22,0xbc48bd7b,0x3d753c95,
0x3cc4bd6d,0x3cf13d62,0xbd7bbc48,0x3d46bd22,0xbd353d35,0xbbc9bd7f,0x3d553d0e,0xbd753c95,0x3d6dbcc4,0xbc953d75,0xbd0ebd55,0x3d7f3bc9,0xbd800000,0x3d22bd46,0x3c483d7b,0xbd62bcf1,
0xbd6dbcc4,0x3d62bcf1,0xbc483d7b,0xbd22bd46,0x3d353d35,0xbd7f3bc9,0x3d0ebd55,0x3c953d75,0xbcc4bd6d,0x3d753c95,0xbd553d0e,0x3bc9bd7f,0x80003d80,0xbd46bd22,0x3d7bbc48,0xbcf13d62,
0x8000bd80,0x3d223d46,0xbd7bbc48,0x3d62bcf1,0xbcc43d6d,0xbc95bd75,0x3d553d0e,0xbd7f3bc9,0x3d35bd35,0xbbc93d7f,0xbd0ebd55,0x3d753c95,0xbd6d3cc4,0x3cf1bd62,0x3c483d7b,0xbd46bd22,
0xbd800000,0x3d46bd22,0xbc483d7b,0xbcf1bd62,0x3d6d3cc4,0xbd753c95,0x3d0ebd55,0x3bc93d7f,0xbd35bd35,0x3d7f3bc9,0xbd553d0e,0x3c95bd75,0x3cc43d6d,0xbd62bcf1,0x3d7bbc48,0xbd223d46,
0x3d6dbcc4,0xbd223d46,0x3c48bd7b,0x3c953d75,0x80003d80,0xbcf1bd62,0x3d553d0e,0xbd7fbbc9,0xbcc43d6d,0xbbc9bd7f,0x3d0e3d55,0xbd62bcf1,0xbd35bd35,0x3d753c95,0xbd7b3c48,0x3d46bd22,
0x3cc43d6d,0xbd46bd22,0x3d7b3c48,0xbd753c95,0xbd800000,0x3d62bcf1,0xbd0e3d55,0x3bc9bd7f,0xbd6dbcc4,0x3d7fbbc9,0xbd553d0e,0x3cf1bd62,0x3d35bd35,0xbc953d75,0xbc48bd7b,0x3d223d46,
0xbd353d35,0x3cf1bd62,0xbc483d7b,0xbbc9bd7f,0x3cc43d6d,0xbd22bd46,0x3d553d0e,0xbd75bc95,0x8000bd80,0x3c953d75,0xbd0ebd55,0x3d463d22,0xbd6dbcc4,0x3d7f3bc9,0xbd7b3c48,0x3d62bcf1,
0x3d353d35,0xbd62bcf1,0x3d7b3c48,0xbd7f3bc9,0x3d6dbcc4,0xbd463d22,0x3d0ebd55,0xbc953d75,0xbd800000,0x3d75bc95,0xbd553d0e,0x3d22bd46,0xbcc43d6d,0x3bc9bd7f,0x3c483d7b,0xbcf1bd62,
0x3d6d3cc4,0xbd75bc95,0x3d7b3c48,0xbd7fbbc9,0x3d353d35,0xbd46bd22,0x3d553d0e,0xbd62bcf1,0x3cc43d6d,0xbcf1bd62,0x3d0e3d55,0xbd22bd46,0x80003d80,0xbbc9bd7f,0x3c483d7b,0xbc95bd75,
0xbcc43d6d,0x3c95bd75,0xbc483d7b,0x3bc9bd7f,0xbd353d35,0x3d22bd46,0xbd0e3d55,0x3cf1bd62,0xbd6d3cc4,0x3d62bcf1,0xbd553d0e,0x3d46bd22,0xbd800000,0x3d7fbbc9,0xbd7b3c48,0x3d75bc95,
0x3d80,0x3bc9bd7f,0xbc483d7b,0x3c95bd75,0xbcc43d6d,0x3cf1bd62,0xbd0e3d55,0x3d22bd46,0xbd353d35,0x3d46bd22,0xbd553d0e,0x3d62bcf1,0xbd6d3cc4,0x3d75bc95,0xbd7b3c48,0x3d7fbbc9,
0xbd800000,0x3d7f3bc9,0xbd7bbc48,0x3d753c95,0xbd6dbcc4,0x3d623cf1,0xbd55bd0e,0x3d463d22,0xbd35bd35,0x3d223d46,0xbd0ebd55,0x3cf13d62,0xbcc4bd6d,0x3c953d75,0xbc48bd7b,0x3bc93d7f,
0xbd6d3cc4,0x3d7fbbc9,0xbd7bbc48,0x3d623cf1,0x3d80,0x3c95bd75,0xbd0e3d55,0x3d46bd22,0x3cc4bd6d,0xbd223d46,0x3d55bd0e,0xbd753c95,0xbd35bd35,0x3cf13d62,0xbc48bd7b,0xbbc93d7f,
0x3cc43d6d,0xbbc9bd7f,0xbc483d7b,0x3cf1bd62,0x3d800000,0xbd75bc95,0x3d553d0e,0xbd22bd46,0xbd6dbcc4,0x3d463d22,0xbd0ebd55,0x3c953d75,0xbd353d35,0x3d62bcf1,0xbd7b3c48,0x3d7f3bc9,
0x3d35bd35,0xbd753c95,0x3d7b3c48,0xbd46bd22,0x3cc43d6d,0x3bc9bd7f,0xbd0e3d55,0x3d62bcf1,0x3d80,0x3cf1bd62,0xbd553d0e,0x3d7fbbc9,0xbd6dbcc4,0x3d223d46,0xbc48bd7b,0xbc953d75,
0x3d353d35,0xbc95bd75,0xbc483d7b,0x3d22bd46,0xbd6d3cc4,0x3d7f3bc9,0xbd55bd0e,0x3cf13d62,0xbd800000,0x3d623cf1,0xbd0ebd55,0x3bc93d7f,0x3cc4bd6d,0xbd463d22,0x3d7bbc48,0xbd75bc95,
0xbd6dbcc4,0x3cf13d62,0x3c48bd7b,0xbd463d22,0x3d353d35,0xbbc9bd7f,0xbd0e3d55,0x3d75bc95,0xbcc4bd6d,0xbc953d75,0x3d55bd0e,0xbd7fbbc9,0x3d80,0x3d22bd46,0xbd7b3c48,0x3d623cf1,
0xbcc43d6d,0x3d62bcf1,0xbd7bbc48,0x3d223d46,0x3d35bd35,0xbd7f3bc9,0x3d553d0e,0xbc95bd75,0xbd6d3cc4,0x3d753c95,0xbd0ebd55,0xbbc93d7f,0x3d800000,0xbd46bd22,0x3c483d7b,0x3cf1bd62,
0xbd800000,0x3d223d46,0x3c48bd7b,0xbd623cf1,0x3d6d3cc4,0xbc95bd75,0xbd0e3d55,0x3d7fbbc9,0xbd35bd35,0xbbc93d7f,0x3d55bd0e,0xbd75bc95,0x3cc43d6d,0x3cf1bd62,0xbd7b3c48,0x3d463d22,
0x3d80,0x3d46bd22,0xbd7bbc48,0x3cf13d62,0x3cc4bd6d,0xbd753c95,0x3d553d0e,0xbbc9bd7f,0xbd353d35,0x3d7f3bc9,0xbd0ebd55,0xbc953d75,0x3d6dbcc4,0xbd62bcf1,0x3c483d7b,0x3d22bd46,
0xbcc4bd6d,0xbd223d46,0x3d7b3c48,0xbc95bd75,0x3d800000,0xbcf1bd62,0xbd0e3d55,0x3d7f3bc9,0x3d6d3cc4,0xbbc9bd7f,0xbd553d0e,0x3d623cf1,0xbd353d35,0x3d753c95,0xbc48bd7b,0xbd463d22,
0x3d6dbcc4,0xbd46bd22,0xbc483d7b,0x3d75bc95,0x3d80,0x3d62bcf1,0xbd55bd0e,0xbbc93d7f,0xbcc43d6d,0x3d7fbbc9,0xbd0ebd55,0xbcf13d62,0xbd35bd35,0xbc953d75,0x3d7bbc48,0xbd22bd46,
0x3d353d35,0x3cf1bd62,0xbd7bbc48,0x3bc93d7f,0x3d6dbcc4,0xbd22bd46,0xbd0e3d55,0x3d753c95,0xbd800000,0x3c953d75,0x3d55bd0e,0xbd46bd22,0xbcc43d6d,0x3d7f3bc9,0xbc48bd7b,0xbd623cf1,
0x3d35bd35,0xbd62bcf1,0xbc483d7b,0x3d7fbbc9,0xbcc4bd6d,0xbd463d22,0x3d553d0e,0x3c95bd75,0x3d80,0x3d75bc95,0xbd0ebd55,0xbd223d46,0x3d6d3cc4,0x3bc9bd7f,0xbd7b3c48,0x3cf13d62,
0x3cc4bd6d,0xbd75bc95,0xbc483d7b,0x3d7f3bc9,0x3d35bd35,0xbd46bd22,0xbd0e3d55,0x3d623cf1,0x3d6dbcc4,0xbcf1bd62,0xbd553d0e,0x3d223d46,0x3d800000,0xbbc9bd7f,0xbd7b3c48,0x3c953d75,
0x3d6d3cc4,0x3c95bd75,0xbd7bbc48,0xbbc93d7f,0x3d353d35,0x3d22bd46,0xbd55bd0e,0xbcf13d62,0x3cc43d6d,0x3d62bcf1,0xbd0ebd55,0xbd463d22,0x3d80,0x3d7fbbc9,0xbc48bd7b,0xbd753c95,
0xbd800000,0x3d7f3bc9,0xbd7bbc48,0x3d753c95,0xbd6dbcc4,0x3d623cf1,0xbd55bd0e,0x3d463d22,0xbd35bd35,0x3d223d46,0xbd0ebd55,0x3cf13d62,0xbcc4bd6d,0x3c953d75,0xbc48bd7b,0x3bc93d7f,
0x8000bd80,0xbbc93d7f,0x3c48bd7b,0xbc953d75,0x3cc4bd6d,0xbcf13d62,0x3d0ebd55,0xbd223d46,0x3d35bd35,0xbd463d22,0x3d55bd0e,0xbd623cf1,0x3d6dbcc4,0xbd753c95,0x3d7bbc48,0xbd7f3bc9,
0xbcc4bd6d,0x3bc93d7f,0x3c48bd7b,0xbcf13d62,0xbd800000,0x3d753c95,0xbd55bd0e,0x3d223d46,0x3d6d3cc4,0xbd46bd22,0x3d0e3d55,0xbc95bd75,0x3d35bd35,0xbd623cf1,0x3d7bbc48,0xbd7fbbc9,
0xbd6d3cc4,0x3d7fbbc9,0xbd7bbc48,0x3d623cf1,0x80003d80,0x3c95bd75,0xbd0e3d55,0x3d46bd22,0x3cc4bd6d,0xbd223d46,0x3d55bd0e,0xbd753c95,0xbd35bd35,0x3cf13d62,0xbc48bd7b,0xbbc93d7f,
0x3d353d35,0xbc95bd75,0xbc483d7b,0x3d22bd46,0xbd6d3cc4,0x3d7f3bc9,0xbd55bd0e,0x3cf13d62,0xbd800000,0x3d623cf1,0xbd0ebd55,0x3bc93d7f,0x3cc4bd6d,0xbd463d22,0x3d7bbc48,0xbd75bc95,
0xbd353d35,0x3d75bc95,0xbd7bbc48,0x3d463d22,0xbcc4bd6d,0xbbc93d7f,0x3d0ebd55,0xbd623cf1,0x8000bd80,0xbcf13d62,0x3d55bd0e,0xbd7f3bc9,0x3d6d3cc4,0xbd22bd46,0x3c483d7b,0x3c95bd75,
0x3cc4bd6d,0xbd623cf1,0x3d7b3c48,0xbd22bd46,0xbd353d35,0x3d7fbbc9,0xbd55bd0e,0x3c953d75,0x3d6dbcc4,0xbd75bc95,0x3d0e3d55,0x3bc9bd7f,0xbd800000,0x3d463d22,0xbc48bd7b,0xbcf13d62,
0xbd6dbcc4,0x3cf13d62,0x3c48bd7b,0xbd463d22,0x3d353d35,0xbbc9bd7f,0xbd0e3d55,0x3d75bc95,0xbcc4bd6d,0xbc953d75,0x3d55bd0e,0xbd7fbbc9,0x80003d80,0x3d22bd46,0xbd7b3c48,0x3d623cf1,
0x8000bd80,0xbd463d22,0x3d7b3c48,0xbcf1bd62,0xbcc43d6d,0x3d75bc95,0xbd55bd0e,0x3bc93d7f,0x3d35bd35,0xbd7fbbc9,0x3d0e3d55,0x3c95bd75,0xbd6d3cc4,0x3d623cf1,0xbc48bd7b,0xbd223d46,
0xbd800000,0x3d223d46,0x3c48bd7b,0xbd623cf1,0x3d6d3cc4,0xbc95bd75,0xbd0e3d55,0x3d7fbbc9,0xbd35bd35,0xbbc93d7f,0x3d55bd0e,0xbd75bc95,0x3cc43d6d,0x3cf1bd62,0xbd7b3c48,0x3d463d22,
0x3d6dbcc4,0xbd46bd22,0xbc483d7b,0x3d75bc95,0x80003d80,0x3d62bcf1,0xbd55bd0e,0xbbc93d7f,0xbcc43d6d,0x3d7fbbc9,0xbd0ebd55,0xbcf13d62,0xbd35bd35,0xbc953d75,0x3d7bbc48,0xbd22bd46,
0x3cc43d6d,0x3d22bd46,0xbd7bbc48,0x3c953d75,0xbd800000,0x3cf13d62,0x3d0ebd55,0xbd7fbbc9,0xbd6dbcc4,0x3bc93d7f,0x3d55bd0e,0xbd62bcf1,0x3d35bd35,0xbd75bc95,0x3c483d7b,0x3d46bd22,
0xbd353d35,0x3d623cf1,0x3c48bd7b,0xbd7f3bc9,0x3cc43d6d,0x3d46bd22,0xbd55bd0e,0xbc953d75,0x8000bd80,0xbd753c95,0x3d0e3d55,0x3d22bd46,0xbd6dbcc4,0xbbc93d7f,0x3d7bbc48,0xbcf1bd62,
0x3d353d35,0x3cf1bd62,0xbd7bbc48,0x3bc93d7f,0x3d6dbcc4,0xbd22bd46,0xbd0e3d55,0x3d753c95,0xbd800000,0x3c953d75,0x3d55bd0e,0xbd46bd22,0xbcc43d6d,0x3d7f3bc9,0xbc48bd7b,0xbd623cf1,
0x3d6d3cc4,0x3c95bd75,0xbd7bbc48,0xbbc93d7f,0x3d353d35,0x3d22bd46,0xbd55bd0e,0xbcf13d62,0x3cc43d6d,0x3d62bcf1,0xbd0ebd55,0xbd463d22,0x80003d80,0x3d7fbbc9,0xbc48bd7b,0xbd753c95,
0xbcc43d6d,0x3d753c95,0x3c48bd7b,0xbd7fbbc9,0xbd353d35,0x3d463d22,0x3d0ebd55,0xbd62bcf1,0xbd6d3cc4,0x3cf13d62,0x3d55bd0e,0xbd22bd46,0xbd800000,0x3bc93d7f,0x3d7bbc48,0xbc95bd75,
0x3d80,0x3d7f3bc9,0x3c48bd7b,0xbd75bc95,0xbcc43d6d,0x3d623cf1,0x3d0ebd55,0xbd46bd22,0xbd353d35,0x3d223d46,0x3d55bd0e,0xbcf1bd62,0xbd6d3cc4,0x3c953d75,0x3d7bbc48,0xbbc9bd7f,
0xbd800000,0xbbc93d7f,0x3d7b3c48,0x3c95bd75,0xbd6dbcc4,0xbcf13d62,0x3d553d0e,0x3d22bd46,0xbd35bd35,0xbd463d22,0x3d0e3d55,0x3d62bcf1,0xbcc4bd6d,0xbd753c95,0x3c483d7b,0x3d7fbbc9,
0xbd6d3cc4,0x3bc93d7f,0x3d7b3c48,0x3cf1bd62,0x3d80,0x3d753c95,0x3d0ebd55,0xbd22bd46,0x3cc4bd6d,0xbd46bd22,0xbd553d0e,0x3c953d75,0xbd35bd35,0xbd623cf1,0x3c483d7b,0x3d7f3bc9,
0x3cc43d6d,0x3d7fbbc9,0x3c48bd7b,0xbd62bcf1,0x3d800000,0x3c95bd75,0xbd55bd0e,0xbd463d22,0xbd6dbcc4,0xbd223d46,0x3d0e3d55,0x3d75bc95,0xbd353d35,0x3cf13d62,0x3d7bbc48,0x3bc9bd7f,
0x3d35bd35,0xbc95bd75,0xbd7bbc48,0xbd223d46,0x3cc43d6d,0x3d7f3bc9,0x3d0ebd55,0xbcf1bd62,0x3d80,0x3d623cf1,0x3d55bd0e,0xbbc9bd7f,0xbd6dbcc4,0xbd463d22,0x3c483d7b,0x3d753c95,
0x3d353d35,0x3d75bc95,0x3c48bd7b,0xbd46bd22,0xbd6d3cc4,0xbbc93d7f,0x3d553d0e,0x3d62bcf1,0xbd800000,0xbcf13d62,0x3d0e3d55,0x3d7fbbc9,0x3cc4bd6d,0xbd22bd46,0xbd7b3c48,0xbc953d75,
0xbd6dbcc4,0xbd623cf1,0xbc483d7b,0x3d223d46,0x3d353d35,0x3d7fbbc9,0x3d0ebd55,0xbc95bd75,0xbcc4bd6d,0xbd75bc95,0xbd553d0e,0xbbc93d7f,0x3d80,0x3d463d22,0x3d7bbc48,0x3cf1bd62,
0xbcc43d6d,0x3cf13d62,0x3d7b3c48,0x3d46bd22,0x3d35bd35,0xbbc9bd7f,0xbd55bd0e,0xbd753c95,0xbd6d3cc4,0xbc953d75,0x3d0e3d55,0x3d7f3bc9,0x3d800000,0x3d22bd46,0xbc48bd7b,0xbd62bcf1,
0xbd800000,0xbd463d22,0xbc483d7b,0x3cf13d62,0x3d6d3cc4,0x3d75bc95,0x3d0ebd55,0xbbc9bd7f,0xbd35bd35,0xbd7fbbc9,0xbd553d0e,0xbc953d75,0x3cc43d6d,0x3d623cf1,0x3d7bbc48,0x3d22bd46,
0x3d80,0x3d223d46,0x3d7b3c48,0x3d62bcf1,0x3cc4bd6d,0xbc95bd75,0xbd55bd0e,0xbd7f3bc9,0xbd353d35,0xbbc93d7f,0x3d0e3d55,0x3d753c95,0x3d6dbcc4,0x3cf1bd62,0xbc48bd7b,0xbd46bd22,
0xbcc4bd6d,0xbd46bd22,0xbd7bbc48,0xbd753c95,0x3d800000,0x3d62bcf1,0x3d0ebd55,0x3bc9bd7f,0x3d6d3cc4,0x3d7fbbc9,0x3d55bd0e,0x3cf1bd62,0xbd353d35,0xbc953d75,0x3c483d7b,0x3d223d46,
0x3d6dbcc4,0x3d22bd46,0x3c48bd7b,0xbc95bd75,0x3d80,0x3cf13d62,0x3d553d0e,0x3d7f3bc9,0xbcc43d6d,0x3bc93d7f,0x3d0e3d55,0x3d623cf1,0xbd35bd35,0xbd75bc95,0xbd7b3c48,0xbd463d22,
0x3d353d35,0x3d623cf1,0x3d7b3c48,0x3d7fbbc9,0x3d6dbcc4,0x3d46bd22,0x3d0ebd55,0x3c95bd75,0xbd800000,0xbd753c95,0xbd553d0e,0xbd223d46,0xbcc43d6d,0xbbc93d7f,0x3c483d7b,0x3cf13d62,
0x3d35bd35,0x3cf1bd62,0x3c48bd7b,0xbbc9bd7f,0xbcc4bd6d,0xbd22bd46,0xbd55bd0e,0xbd75bc95,0x3d80,0x3c953d75,0x3d0e3d55,0x3d463d22,0x3d6d3cc4,0x3d7f3bc9,0x3d7bbc48,0x3d62bcf1,
0x3cc4bd6d,0x3c95bd75,0x3c48bd7b,0x3bc9bd7f,0x3d35bd35,0x3d22bd46,0x3d0ebd55,0x3cf1bd62,0x3d6dbcc4,0x3d62bcf1,0x3d55bd0e,0x3d46bd22,0x3d800000,0x3d7fbbc9,0x3d7bbc48,0x3d75bc95,
0x3d6d3cc4,0x3d753c95,0x3d7b3c48,0x3d7f3bc9,0x3d353d35,0x3d463d22,0x3d553d0e,0x3d623cf1,0x3cc43d6d,0x3cf13d62,0x3d0e3d55,0x3d223d46,0x3d80,0x3bc93d7f,0x3c483d7b,0x3c953d75,
0xbd800000,0xbbc93d7f,0x3d7b3c48,0x3c95bd75,0xbd6dbcc4,0xbcf13d62,0x3d553d0e,0x3d22bd46,0xbd35bd35,0xbd463d22,0x3d0e3d55,0x3d62bcf1,0xbcc4bd6d,0xbd753c95,0x3c483d7b,0x3d7fbbc9,
0x8000bd80,0xbd7fbbc9,0xbc483d7b,0x3d753c95,0x3cc4bd6d,0xbd62bcf1,0xbd0e3d55,0x3d463d22,0x3d35bd35,0xbd22bd46,0xbd553d0e,0x3cf13d62,0x3d6dbcc4,0xbc95bd75,0xbd7b3c48,0x3bc93d7f,
0xbcc4bd6d,0xbd7f3bc9,0xbc483d7b,0x3d623cf1,0xbd800000,0xbc953d75,0x3d553d0e,0x3d46bd22,0x3d6d3cc4,0x3d22bd46,0xbd0ebd55,0xbd753c95,0x3d35bd35,0xbcf1bd62,0xbd7b3c48,0xbbc93d7f,
0xbd6d3cc4,0x3bc93d7f,0x3d7b3c48,0x3cf1bd62,0x80003d80,0x3d753c95,0x3d0ebd55,0xbd22bd46,0x3cc4bd6d,0xbd46bd22,0xbd553d0e,0x3c953d75,0xbd35bd35,0xbd623cf1,0x3c483d7b,0x3d7f3bc9,
0x3d353d35,0x3d75bc95,0x3c48bd7b,0xbd46bd22,0xbd6d3cc4,0xbbc93d7f,0x3d553d0e,0x3d62bcf1,0xbd800000,0xbcf13d62,0x3d0e3d55,0x3d7fbbc9,0x3cc4bd6d,0xbd22bd46,0xbd7b3c48,0xbc953d75,
0xbd353d35,0x3c953d75,0x3d7b3c48,0x3d22bd46,0xbcc4bd6d,0xbd7fbbc9,0xbd0e3d55,0x3cf13d62,0x8000bd80,0xbd62bcf1,0xbd553d0e,0x3bc93d7f,0x3d6d3cc4,0x3d46bd22,0xbc48bd7b,0xbd75bc95,
0x3cc4bd6d,0xbcf1bd62,0xbd7bbc48,0xbd463d22,0xbd353d35,0x3bc93d7f,0x3d553d0e,0x3d75bc95,0x3d6dbcc4,0x3c95bd75,0xbd0ebd55,0xbd7fbbc9,0xbd800000,0xbd223d46,0x3c483d7b,0x3d623cf1,
0xbd6dbcc4,0xbd623cf1,0xbc483d7b,0x3d223d46,0x3d353d35,0x3d7fbbc9,0x3d0ebd55,0xbc95bd75,0xbcc4bd6d,0xbd75bc95,0xbd553d0e,0xbbc93d7f,0x80003d80,0x3d463d22,0x3d7bbc48,0x3cf1bd62,
0x8000bd80,0xbd22bd46,0xbd7bbc48,0xbd623cf1,0xbcc43d6d,0x3c953d75,0x3d553d0e,0x3d7fbbc9,0x3d35bd35,0x3bc9bd7f,0xbd0ebd55,0xbd75bc95,0xbd6d3cc4,0xbcf13d62,0x3c483d7b,0x3d463d22,
0xbd800000,0xbd463d22,0xbc483d7b,0x3cf13d62,0x3d6d3cc4,0x3d75bc95,0x3d0ebd55,0xbbc9bd7f,0xbd35bd35,0xbd7fbbc9,0xbd553d0e,0xbc953d75,0x3cc43d6d,0x3d623cf1,0x3d7bbc48,0x3d22bd46,
0x3d6dbcc4,0x3d22bd46,0x3c48bd7b,0xbc95bd75,0x80003d80,0x3cf13d62,0x3d553d0e,0x3d7f3bc9,0xbcc43d6d,0x3bc93d7f,0x3d0e3d55,0x3d623cf1,0xbd35bd35,0xbd75bc95,0xbd7b3c48,0xbd463d22,
0x3cc43d6d,0x3d463d22,0x3d7b3c48,0x3d75bc95,0xbd800000,0xbd623cf1,0xbd0e3d55,0xbbc93d7f,0xbd6dbcc4,0xbd7f3bc9,0xbd553d0e,0xbcf13d62,0x3d35bd35,0x3c95bd75,0xbc48bd7b,0xbd22bd46,
0xbd353d35,0xbcf13d62,0xbc483d7b,0x3bc93d7f,0x3cc43d6d,0x3d223d46,0x3d553d0e,0x3d753c95,0x8000bd80,0xbc95bd75,0xbd0ebd55,0xbd46bd22,0xbd6dbcc4,0xbd7fbbc9,0xbd7b3c48,0xbd623cf1,
0x3d353d35,0x3d623cf1,0x3d7b3c48,0x3d7fbbc9,0x3d6dbcc4,0x3d46bd22,0x3d0ebd55,0x3c95bd75,0xbd800000,0xbd753c95,0xbd553d0e,0xbd223d46,0xbcc43d6d,0xbbc93d7f,0x3c483d7b,0x3cf13d62,
0x3d6d3cc4,0x3d753c95,0x3d7b3c48,0x3d7f3bc9,0x3d353d35,0x3d463d22,0x3d553d0e,0x3d623cf1,0x3cc43d6d,0x3cf13d62,0x3d0e3d55,0x3d223d46,0x80003d80,0x3bc93d7f,0x3c483d7b,0x3c953d75,
0xbcc43d6d,0xbc953d75,0xbc483d7b,0xbbc93d7f,0xbd353d35,0xbd223d46,0xbd0e3d55,0xbcf13d62,0xbd6d3cc4,0xbd623cf1,0xbd553d0e,0xbd463d22,0xbd800000,0xbd7f3bc9,0xbd7b3c48,0xbd753c95,
0x3d80,0xbc163d7d,0xbc953d75,0xbcdb3d67,0xbd0e3d55,0xbd2c3d3e,0xbd463d22,0xbd5c3d04,0xbd6d3cc4,0xbd783c79,0xbd7f3bc9,0xbd80bb49,0xbd7bbc48,0xbd71bcac,0xbd62bcf1,0xbd4ebd18,
0xbd35bd35,0xbd18bd4e,0xbcf1bd62,0xbcacbd71,0xbc48bd7b,0xbb49bd80,0x3bc9bd7f,0x3c79bd78,0x3cc4bd6d,0x3d04bd5c,0x3d22bd46,0x3d3ebd2c,0x3d55bd0e,0x3d67bcdb,0x3d75bc95,0x3d7dbc16,
0xbd7b3c48,0xbd7dbc16,0xbd62bcf1,0xbd2cbd3e,0x3d80,0xbcac3d71,0xbd223d46,0xbd5c3d04,0x3d55bd0e,0x3d78bc79,0x3d7f3bc9,0x3d673cdb,0xbcc4bd6d,0xbb49bd80,0x3c95bd75,0x3d18bd4e,
0xbd0e3d55,0xbd4e3d18,0xbd753c95,0xbd80bb49,0x3d353d35,0x3cdb3d67,0x3bc93d7f,0xbc793d78,0x3c48bd7b,0x3d04bd5c,0x3d46bd22,0x3d71bcac,0xbd6dbcc4,0xbd3ebd2c,0xbcf1bd62,0xbc16bd7d,
0x3d6dbcc4,0x3d7d3c16,0x3d463d22,0x3cac3d71,0xbc483d7b,0xbd2c3d3e,0xbd753c95,0xbd78bc79,0x3d80,0xbd043d5c,0xbd623cf1,0xbd80bb49,0xbd55bd0e,0xbcdbbd67,0x3bc9bd7f,0x3d18bd4e,
0xbcc43d6d,0xbd4e3d18,0xbd7f3bc9,0xbd67bcdb,0xbd0ebd55,0xbb49bd80,0x3cf1bd62,0x3d5cbd04,0xbd35bd35,0xbc79bd78,0x3c95bd75,0x3d3ebd2c,0x3d7bbc48,0x3d713cac,0x3d223d46,0x3c163d7d,
0xbd0ebd55,0x3c16bd7d,0x3d46bd22,0x3d803b49,0x3cc43d6d,0xbcac3d71,0xbd623cf1,0xbd78bc79,0xbc48bd7b,0x3d04bd5c,0x3d75bc95,0x3d673cdb,0x3d80,0xbd2c3d3e,0xbd7f3bc9,0xbd4ebd18,
0xbd7bbc48,0xbd18bd4e,0x3bc9bd7f,0x3d3ebd2c,0x3d6d3cc4,0x3cdb3d67,0xbc953d75,0xbd5c3d04,0xbd55bd0e,0xbc79bd78,0x3cf1bd62,0x3d71bcac,0x3d353d35,0x3b493d80,0xbd223d46,0xbd7d3c16,
0xbd35bd35,0x3c16bd7d,0x3d62bcf1,0x3d673cdb,0x3c483d7b,0xbd2c3d3e,0xbd7fbbc9,0xbd04bd5c,0x3cc4bd6d,0x3d78bc79,0x3d463d22,0xbb493d80,0xbd553d0e,0xbd71bcac,0xbc95bd75,0x3d18bd4e,
0x3d80,0xbd4e3d18,0xbd75bc95,0xbcacbd71,0x3d0ebd55,0x3d80bb49,0x3d223d46,0xbc793d78,0xbd6d3cc4,0xbd5cbd04,0xbbc9bd7f,0x3d3ebd2c,0x3d7b3c48,0x3cdb3d67,0xbcf13d62,0xbd7d3c16,
0x3d0ebd55,0x3d7d3c16,0x3c953d75,0xbd3e3d2c,0x3d353d35,0xbcac3d71,0xbd7f3bc9,0xbd04bd5c,0xbc483d7b,0xbd783c79,0xbd22bd46,0x3cdbbd67,0xbd6dbcc4,0xbb49bd80,0x3d62bcf1,0x3d4e3d18,
0x3d7bbc48,0x3d183d4e,0xbcf13d62,0xbd80bb49,0x3d80,0xbd673cdb,0xbd46bd22,0x3c79bd78,0xbd553d0e,0xbd5cbd04,0x3bc9bd7f,0x3d71bcac,0xbcc4bd6d,0x3d2cbd3e,0x3d753c95,0x3c163d7d,
0xbcc43d6d,0xbd7dbc16,0xbbc9bd7f,0x3d71bcac,0x3d0e3d55,0xbd2c3d3e,0xbd62bcf1,0x3c79bd78,0xbd35bd35,0x3d04bd5c,0x3d753c95,0xbb493d80,0xbd7b3c48,0xbcdbbd67,0x3d46bd22,0x3d4e3d18,
0x3d6dbcc4,0x3d183d4e,0xbd223d46,0xbd67bcdb,0x3c48bd7b,0x3d80bb49,0x3c953d75,0xbd5c3d04,0x3d80,0xbd783c79,0xbcf1bd62,0x3d3ebd2c,0x3d553d0e,0xbcac3d71,0xbd7fbbc9,0xbc16bd7d,
0x3d7b3c48,0xbc163d7d,0xbd7fbbc9,0x3b49bd80,0x3d6d3cc4,0xbcac3d71,0xbd75bc95,0x3c79bd78,0x3d553d0e,0xbd043d5c,0xbd62bcf1,0x3cdbbd67,0x3d353d35,0xbd2c3d3e,0xbd46bd22,0x3d18bd4e,
0x3d0e3d55,0xbd4e3d18,0xbd22bd46,0x3d3ebd2c,0x3cc43d6d,0xbd673cdb,0xbcf1bd62,0x3d5cbd04,0x3c483d7b,0xbd783c79,0xbc95bd75,0x3d71bcac,0x3d80,0xbd803b49,0xbbc9bd7f,0x3d7dbc16,
0xbd800000,0xbd7dbc16,0xbd75bc95,0xbd67bcdb,0xbd55bd0e,0xbd3ebd2c,0xbd22bd46,0xbd04bd5c,0xbcc4bd6d,0xbc79bd78,0xbbc9bd7f,0x3b49bd80,0x3c48bd7b,0x3cacbd71,0x3cf1bd62,0x3d18bd4e,
0x3d35bd35,0x3d4ebd18,0x3d62bcf1,0x3d71bcac,0x3d7bbc48,0x3d80bb49,0x3d7f3bc9,0x3d783c79,0x3d6d3cc4,0x3d5c3d04,0x3d463d22,0x3d2c3d3e,0x3d0e3d55,0x3cdb3d67,0x3c953d75,0x3c163d7d,
0xbc48bd7b,0x3c16bd7d,0x3cf1bd62,0x3d3ebd2c,0xbd800000,0xbd71bcac,0xbd46bd22,0xbd04bd5c,0x3d0e3d55,0x3c793d78,0xbbc93d7f,0xbcdb3d67,0x3d6dbcc4,0x3d80bb49,0x3d753c95,0x3d4e3d18,
0xbd55bd0e,0xbd18bd4e,0xbc95bd75,0x3b49bd80,0xbd353d35,0xbd673cdb,0xbd7f3bc9,0xbd78bc79,0x3d7b3c48,0x3d5c3d04,0x3d223d46,0x3cac3d71,0x3cc4bd6d,0x3d2cbd3e,0x3d62bcf1,0x3d7dbc16,
0x3cc43d6d,0xbc163d7d,0xbd223d46,0xbd713cac,0xbd7bbc48,0xbd3ebd2c,0xbc95bd75,0x3c79bd78,0xbd800000,0xbd5cbd04,0xbcf1bd62,0x3b49bd80,0x3d0ebd55,0x3d67bcdb,0x3d7f3bc9,0x3d4e3d18,
0xbd6dbcc4,0xbd18bd4e,0xbbc9bd7f,0x3cdbbd67,0x3d55bd0e,0x3d80bb49,0x3d623cf1,0x3d043d5c,0x3d35bd35,0x3d78bc79,0x3d753c95,0x3d2c3d3e,0x3c483d7b,0xbcac3d71,0xbd463d22,0xbd7d3c16,
0x3d55bd0e,0x3d7d3c16,0x3d223d46,0xbb493d80,0xbd6d3cc4,0xbd71bcac,0xbcf1bd62,0x3c79bd78,0x3d7bbc48,0x3d5c3d04,0x3c953d75,0xbcdb3d67,0xbd800000,0xbd3ebd2c,0xbbc9bd7f,0x3d18bd4e,
0x3c48bd7b,0x3d4ebd18,0x3d7f3bc9,0x3d2c3d3e,0xbcc43d6d,0xbd673cdb,0xbd75bc95,0xbd04bd5c,0x3d0ebd55,0x3d78bc79,0x3d623cf1,0x3cac3d71,0xbd353d35,0xbd803b49,0xbd46bd22,0xbc16bd7d,
0x3d35bd35,0x3d7d3c16,0x3cf13d62,0xbcdb3d67,0xbd7b3c48,0xbd3ebd2c,0x3bc9bd7f,0x3d5cbd04,0x3d6d3cc4,0x3c793d78,0xbd223d46,0xbd80bb49,0xbd0ebd55,0x3cacbd71,0x3d75bc95,0x3d4e3d18,
0xbd800000,0xbd18bd4e,0x3c95bd75,0x3d71bcac,0x3d553d0e,0x3b493d80,0xbd463d22,0xbd78bc79,0xbcc4bd6d,0x3d04bd5c,0x3d7fbbc9,0x3d2c3d3e,0xbc483d7b,0xbd673cdb,0xbd62bcf1,0xbc16bd7d,
0x3d553d0e,0xbc163d7d,0xbd753c95,0xbd2cbd3e,0xbd353d35,0xbd71bcac,0xbbc9bd7f,0x3d5cbd04,0xbd7bbc48,0xbc79bd78,0x3d46bd22,0x3d673cdb,0x3cc4bd6d,0x3d80bb49,0x3cf13d62,0xbd183d4e,
0x3c483d7b,0xbd4e3d18,0xbd62bcf1,0x3b49bd80,0xbd800000,0xbcdbbd67,0x3d22bd46,0x3d783c79,0xbd0ebd55,0x3d04bd5c,0x3d7f3bc9,0x3cac3d71,0x3d6dbcc4,0x3d3e3d2c,0xbc953d75,0xbd7d3c16,
0xbd6dbcc4,0x3c16bd7d,0x3d7fbbc9,0x3cac3d71,0xbd553d0e,0xbd3ebd2c,0x3cf1bd62,0x3d783c79,0x3d35bd35,0x3d5c3d04,0xbc953d75,0xbd80bb49,0xbc48bd7b,0x3d67bcdb,0x3d223d46,0xbd183d4e,
0x3cc43d6d,0xbd4e3d18,0xbd46bd22,0x3cdbbd67,0x3d7b3c48,0x3b493d80,0xbd753c95,0xbd04bd5c,0xbd800000,0xbc79bd78,0x3d62bcf1,0x3d2c3d3e,0xbd0e3d55,0xbd71bcac,0x3bc9bd7f,0x3d7dbc16,
0xbc483d7b,0xbd7dbc16,0x3bc9bd7f,0x3d803b49,0xbcc43d6d,0xbd71bcac,0x3c95bd75,0x3d783c79,0xbd0e3d55,0xbd5cbd04,0x3cf1bd62,0x3d673cdb,0xbd353d35,0xbd3ebd2c,0x3d22bd46,0x3d4e3d18,
0xbd553d0e,0xbd18bd4e,0x3d46bd22,0x3d2c3d3e,0xbd6d3cc4,0xbcdbbd67,0x3d62bcf1,0x3d043d5c,0xbd7b3c48,0xbc79bd78,0x3d75bc95,0x3cac3d71,0xbd800000,0xbb49bd80,0x3d7fbbc9,0x3c163d7d,
0x3d80,0xbd7dbc16,0x3c95bd75,0x3d673cdb,0xbd0e3d55,0xbd3ebd2c,0x3d46bd22,0x3d043d5c,0xbd6d3cc4,0xbc79bd78,0x3d7fbbc9,0xbb493d80,0xbd7bbc48,0x3cacbd71,0x3d623cf1,0xbd183d4e,
0xbd35bd35,0x3d4ebd18,0x3cf13d62,0xbd713cac,0xbc48bd7b,0x3d80bb49,0xbbc93d7f,0xbd78bc79,0x3cc4bd6d,0x3d5c3d04,0xbd223d46,0xbd2cbd3e,0x3d55bd0e,0x3cdb3d67,0xbd753c95,0xbc16bd7d,
0xbd7b3c48,0x3c16bd7d,0x3d623cf1,0xbd3e3d2c,0x3d80,0xbd71bcac,0x3d22bd46,0x3d043d5c,0x3d55bd0e,0x3c793d78,0xbd7fbbc9,0x3cdbbd67,0xbcc4bd6d,0x3d80bb49,0xbc953d75,0xbd4ebd18,
0xbd0e3d55,0xbd18bd4e,0x3d75bc95,0xbb493d80,0x3d353d35,0xbd673cdb,0xbbc9bd7f,0x3d783c79,0x3c48bd7b,0x3d5c3d04,0xbd463d22,0xbcacbd71,0xbd6dbcc4,0x3d2cbd3e,0x3cf13d62,0xbd7d3c16,
0x3d6dbcc4,0xbc163d7d,0xbd46bd22,0x3d71bcac,0xbc483d7b,0xbd3ebd2c,0x3d75bc95,0xbc793d78,0x3d80,0xbd5cbd04,0x3d62bcf1,0xbb493d80,0xbd55bd0e,0x3d67bcdb,0xbbc93d7f,0xbd4ebd18,
0xbcc43d6d,0xbd18bd4e,0x3d7fbbc9,0xbcdb3d67,0xbd0ebd55,0x3d80bb49,0xbcf13d62,0xbd04bd5c,0xbd35bd35,0x3d78bc79,0xbc953d75,0xbd2cbd3e,0x3d7bbc48,0xbcac3d71,0xbd22bd46,0x3d7dbc16,
0xbd0ebd55,0x3d7d3c16,0xbd463d22,0x3b49bd80,0x3cc43d6d,0xbd71bcac,0x3d62bcf1,0xbc793d78,0xbc48bd7b,0x3d5c3d04,0xbd753c95,0x3cdbbd67,0x3d80,0xbd3ebd2c,0x3d7fbbc9,0xbd183d4e,
0xbd7bbc48,0x3d4ebd18,0xbbc93d7f,0xbd2cbd3e,0x3d6d3cc4,0xbd673cdb,0x3c95bd75,0x3d043d5c,0xbd55bd0e,0x3d78bc79,0xbcf13d62,0xbcacbd71,0x3d353d35,0xbd803b49,0x3d22bd46,0x3c163d7d,
0xbd35bd35,0x3d7d3c16,0xbd623cf1,0x3cdbbd67,0x3c483d7b,0xbd3ebd2c,0x3d7f3bc9,0xbd5c3d04,0x3cc4bd6d,0x3c793d78,0xbd46bd22,0x3d803b49,0xbd553d0e,0x3cacbd71,0x3c953d75,0xbd4ebd18,
0x3d80,0xbd18bd4e,0x3d753c95,0xbd713cac,0x3d0ebd55,0x3b493d80,0xbd22bd46,0x3d783c79,0xbd6d3cc4,0x3d04bd5c,0x3bc93d7f,0xbd2cbd3e,0x3d7b3c48,0xbd673cdb,0x3cf1bd62,0x3c163d7d,
0x3d0ebd55,0xbc163d7d,0xbc95bd75,0x3d2c3d3e,0x3d353d35,0xbd71bcac,0x3d7fbbc9,0xbd5c3d04,0xbc483d7b,0xbc79bd78,0x3d223d46,0xbd67bcdb,0xbd6dbcc4,0x3d80bb49,0xbd623cf1,0x3d18bd4e,
0x3d7bbc48,0xbd4e3d18,0x3cf1bd62,0xbb493d80,0x3d80,0xbcdbbd67,0x3d463d22,0xbd78bc79,0xbd553d0e,0x3d04bd5c,0xbbc93d7f,0xbcacbd71,0xbcc4bd6d,0x3d3e3d2c,0xbd75bc95,0x3d7dbc16,
0xbcc43d6d,0x3c16bd7d,0x3bc93d7f,0xbcacbd71,0x3d0e3d55,0xbd3ebd2c,0x3d623cf1,0xbd78bc79,0xbd35bd35,0x3d5c3d04,0xbd75bc95,0x3d803b49,0xbd7b3c48,0x3d67bcdb,0xbd463d22,0x3d18bd4e,
0x3d6dbcc4,0xbd4e3d18,0x3d22bd46,0xbcdb3d67,0x3c48bd7b,0x3b493d80,0xbc95bd75,0x3d043d5c,0x3d80,0xbc79bd78,0x3cf13d62,0xbd2cbd3e,0x3d553d0e,0xbd71bcac,0x3d7f3bc9,0xbd7d3c16,
0x3d7b3c48,0xbd7dbc16,0x3d7f3bc9,0xbd80bb49,0x3d6d3cc4,0xbd71bcac,0x3d753c95,0xbd78bc79,0x3d553d0e,0xbd5cbd04,0x3d623cf1,0xbd67bcdb,0x3d353d35,0xbd3ebd2c,0x3d463d22,0xbd4ebd18,
0x3d0e3d55,0xbd18bd4e,0x3d223d46,0xbd2cbd3e,0x3cc43d6d,0xbcdbbd67,0x3cf13d62,0xbd04bd5c,0x3c483d7b,0xbc79bd78,0x3c953d75,0xbcacbd71,0x3d80,0xbb49bd80,0x3bc93d7f,0xbc16bd7d,
0xbd800000,0x3c16bd7d,0x3d753c95,0xbcdb3d67,0xbd55bd0e,0x3d2cbd3e,0x3d223d46,0xbd5c3d04,0xbcc4bd6d,0x3d78bc79,0x3bc93d7f,0xbd80bb49,0x3c48bd7b,0x3d713cac,0xbcf13d62,0xbd4ebd18,
0x3d35bd35,0x3d183d4e,0xbd623cf1,0xbcacbd71,0x3d7bbc48,0x3b493d80,0xbd7fbbc9,0x3c79bd78,0x3d6d3cc4,0xbd043d5c,0xbd46bd22,0x3d3ebd2c,0x3d0e3d55,0xbd673cdb,0xbc95bd75,0x3d7dbc16,
0xbc48bd7b,0x3d7d3c16,0xbcf13d62,0xbd2cbd3e,0xbd800000,0x3cacbd71,0x3d463d22,0xbd5c3d04,0x3d0e3d55,0xbd783c79,0x3bc9bd7f,0x3d673cdb,0x3d6dbcc4,0x3b493d80,0xbd75bc95,0x3d18bd4e,
0xbd55bd0e,0x3d4ebd18,0x3c953d75,0xbd80bb49,0xbd353d35,0xbcdbbd67,0x3d7fbbc9,0xbc793d78,0x3d7b3c48,0xbd043d5c,0xbd22bd46,0x3d71bcac,0x3cc4bd6d,0x3d3e3d2c,0xbd623cf1,0xbc16bd7d,
0x3cc43d6d,0xbd7dbc16,0x3d22bd46,0x3cac3d71,0xbd7bbc48,0x3d2cbd3e,0x3c953d75,0xbd78bc79,0xbd800000,0x3d04bd5c,0x3cf13d62,0xbd80bb49,0x3d0ebd55,0x3cdb3d67,0xbd7fbbc9,0x3d18bd4e,
0xbd6dbcc4,0x3d4ebd18,0x3bc93d7f,0xbd67bcdb,0x3d55bd0e,0x3b493d80,0xbd62bcf1,0x3d5cbd04,0x3d35bd35,0x3c793d78,0xbd75bc95,0x3d3ebd2c,0x3c483d7b,0xbd71bcac,0x3d46bd22,0x3c163d7d,
0x3d55bd0e,0xbc163d7d,0xbd22bd46,0x3d803b49,0xbd6d3cc4,0x3cacbd71,0x3cf13d62,0xbd78bc79,0x3d7bbc48,0xbd043d5c,0xbc95bd75,0x3d673cdb,0xbd800000,0x3d2cbd3e,0x3bc93d7f,0xbd4ebd18,
0x3c48bd7b,0x3d183d4e,0xbd7fbbc9,0x3d3ebd2c,0xbcc43d6d,0xbcdbbd67,0x3d753c95,0xbd5c3d04,0x3d0ebd55,0x3c793d78,0xbd62bcf1,0x3d71bcac,0xbd353d35,0xbb49bd80,0x3d463d22,0xbd7d3c16,
0x3d35bd35,0xbc163d7d,0xbcf1bd62,0x3d673cdb,0xbd7b3c48,0x3d2cbd3e,0xbbc93d7f,0xbd04bd5c,0x3d6d3cc4,0xbd783c79,0x3d22bd46,0xbb493d80,0xbd0ebd55,0x3d713cac,0xbd753c95,0x3d18bd4e,
0xbd800000,0x3d4ebd18,0xbc953d75,0xbcacbd71,0x3d553d0e,0xbd803b49,0x3d46bd22,0xbc793d78,0xbcc4bd6d,0x3d5c3d04,0xbd7f3bc9,0x3d3ebd2c,0xbc483d7b,0xbcdbbd67,0x3d623cf1,0xbd7d3c16,
0x3d553d0e,0xbd7dbc16,0x3d75bc95,0xbd3e3d2c,0xbd353d35,0x3cacbd71,0x3bc93d7f,0xbd04bd5c,0xbd7bbc48,0x3d78bc79,0xbd463d22,0x3cdbbd67,0x3cc4bd6d,0x3b493d80,0xbcf1bd62,0x3d4e3d18,
0x3c483d7b,0xbd18bd4e,0x3d623cf1,0xbd80bb49,0xbd800000,0x3d67bcdb,0xbd223d46,0x3c79bd78,0xbd0ebd55,0x3d5c3d04,0xbd7fbbc9,0x3d71bcac,0x3d6dbcc4,0xbd2c3d3e,0x3c95bd75,0x3c163d7d,
0xbd6dbcc4,0x3d7d3c16,0xbd7f3bc9,0x3d71bcac,0xbd553d0e,0x3d2cbd3e,0xbcf13d62,0x3c79bd78,0x3d35bd35,0xbd043d5c,0x3c95bd75,0xbb493d80,0xbc48bd7b,0x3cdb3d67,0xbd22bd46,0x3d4e3d18,
0x3cc43d6d,0xbd18bd4e,0x3d463d22,0xbd67bcdb,0x3d7b3c48,0xbd803b49,0x3d75bc95,0xbd5c3d04,0xbd800000,0x3d78bc79,0xbd623cf1,0x3d3ebd2c,0xbd0e3d55,0x3cacbd71,0xbbc93d7f,0xbc16bd7d,
0xbc483d7b,0x3c16bd7d,0xbbc93d7f,0x3b49bd80,0xbcc43d6d,0x3cacbd71,0xbc953d75,0x3c79bd78,0xbd0e3d55,0x3d04bd5c,0xbcf13d62,0x3cdbbd67,0xbd353d35,0x3d2cbd3e,0xbd223d46,0x3d18bd4e,
0xbd553d0e,0x3d4ebd18,0xbd463d22,0x3d3ebd2c,0xbd6d3cc4,0x3d67bcdb,0xbd623cf1,0x3d5cbd04,0xbd7b3c48,0x3d78bc79,0xbd753c95,0x3d71bcac,0xbd800000,0x3d80bb49,0xbd7f3bc9,0x3d7dbc16,
0x3d80,0x3c16bd7d,0xbc953d75,0x3cdbbd67,0xbd0e3d55,0x3d2cbd3e,0xbd463d22,0x3d5cbd04,0xbd6d3cc4,0x3d78bc79,0xbd7f3bc9,0x3d803b49,0xbd7bbc48,0x3d713cac,0xbd62bcf1,0x3d4e3d18,
0xbd35bd35,0x3d183d4e,0xbcf1bd62,0x3cac3d71,0xbc48bd7b,0x3b493d80,0x3bc9bd7f,0xbc793d78,0x3cc4bd6d,0xbd043d5c,0x3d22bd46,0xbd3e3d2c,0x3d55bd0e,0xbd673cdb,0x3d75bc95,0xbd7d3c16,
0xbd7b3c48,0x3d7d3c16,0xbd62bcf1,0x3d2c3d3e,0x3d80,0x3cacbd71,0xbd223d46,0x3d5cbd04,0x3d55bd0e,0xbd783c79,0x3d7f3bc9,0xbd67bcdb,0xbcc4bd6d,0x3b493d80,0x3c95bd75,0xbd183d4e,
0xbd0e3d55,0x3d4ebd18,0xbd753c95,0x3d803b49,0x3d353d35,0xbcdbbd67,0x3bc93d7f,0x3c79bd78,0x3c48bd7b,0xbd043d5c,0x3d46bd22,0xbd713cac,0xbd6dbcc4,0x3d3e3d2c,0xbcf1bd62,0x3c163d7d,
0x3d6dbcc4,0xbd7dbc16,0x3d463d22,0xbcacbd71,0xbc483d7b,0x3d2cbd3e,0xbd753c95,0x3d783c79,0x3d80,0x3d04bd5c,0xbd623cf1,0x3d803b49,0xbd55bd0e,0x3cdb3d67,0x3bc9bd7f,0xbd183d4e,
0xbcc43d6d,0x3d4ebd18,0xbd7f3bc9,0x3d673cdb,0xbd0ebd55,0x3b493d80,0x3cf1bd62,0xbd5c3d04,0xbd35bd35,0x3c793d78,0x3c95bd75,0xbd3e3d2c,0x3d7bbc48,0xbd71bcac,0x3d223d46,0xbc16bd7d,
0xbd0ebd55,0xbc163d7d,0x3d46bd22,0xbd80bb49,0x3cc43d6d,0x3cacbd71,0xbd623cf1,0x3d783c79,0xbc48bd7b,0xbd043d5c,0x3d75bc95,0xbd67bcdb,0x3d80,0x3d2cbd3e,0xbd7f3bc9,0x3d4e3d18,
0xbd7bbc48,0x3d183d4e,0x3bc9bd7f,0xbd3e3d2c,0x3d6d3cc4,0xbcdbbd67,0xbc953d75,0x3d5cbd04,0xbd55bd0e,0x3c793d78,0x3cf1bd62,0xbd713cac,0x3d353d35,0xbb49bd80,0xbd223d46,0x3d7dbc16,
0xbd35bd35,0xbc163d7d,0x3d62bcf1,0xbd67bcdb,0x3c483d7b,0x3d2cbd3e,0xbd7fbbc9,0x3d043d5c,0x3cc4bd6d,0xbd783c79,0x3d463d22,0x3b49bd80,0xbd553d0e,0x3d713cac,0xbc95bd75,0xbd183d4e,
0x3d80,0x3d4ebd18,0xbd75bc95,0x3cac3d71,0x3d0ebd55,0xbd803b49,0x3d223d46,0x3c79bd78,0xbd6d3cc4,0x3d5c3d04,0xbbc9bd7f,0xbd3e3d2c,0x3d7b3c48,0xbcdbbd67,0xbcf13d62,0x3d7dbc16,
0x3d0ebd55,0xbd7dbc16,0x3c953d75,0x3d3ebd2c,0x3d353d35,0x3cacbd71,0xbd7f3bc9,0x3d043d5c,0xbc483d7b,0x3d78bc79,0xbd22bd46,0xbcdb3d67,0xbd6dbcc4,0x3b493d80,0x3d62bcf1,0xbd4ebd18,
0x3d7bbc48,0xbd18bd4e,0xbcf13d62,0x3d803b49,0x3d80,0x3d67bcdb,0xbd46bd22,0xbc793d78,0xbd553d0e,0x3d5c3d04,0x3bc9bd7f,0xbd713cac,0xbcc4bd6d,0xbd2c3d3e,0x3d753c95,0xbc16bd7d,
0xbcc43d6d,0x3d7d3c16,0xbbc9bd7f,0xbd713cac,0x3d0e3d55,0x3d2cbd3e,0xbd62bcf1,0xbc793d78,0xbd35bd35,0xbd043d5c,0x3d753c95,0x3b49bd80,0xbd7b3c48,0x3cdb3d67,0x3d46bd22,0xbd4ebd18,
0x3d6dbcc4,0xbd18bd4e,0xbd223d46,0x3d673cdb,0x3c48bd7b,0xbd803b49,0x3c953d75,0x3d5cbd04,0x3d80,0x3d78bc79,0xbcf1bd62,0xbd3e3d2c,0x3d553d0e,0x3cacbd71,0xbd7fbbc9,0x3c163d7d,
0x3d7b3c48,0x3c16bd7d,0xbd7fbbc9,0xbb493d80,0x3d6d3cc4,0x3cacbd71,0xbd75bc95,0xbc793d78,0x3d553d0e,0x3d04bd5c,0xbd62bcf1,0xbcdb3d67,0x3d353d35,0x3d2cbd3e,0xbd46bd22,0xbd183d4e,
0x3d0e3d55,0x3d4ebd18,0xbd22bd46,0xbd3e3d2c,0x3cc43d6d,0x3d67bcdb,0xbcf1bd62,0xbd5c3d04,0x3c483d7b,0x3d78bc79,0xbc95bd75,0xbd713cac,0x3d80,0x3d80bb49,0xbbc9bd7f,0xbd7d3c16,
0xbd800000,0x3d7d3c16,0xbd75bc95,0x3d673cdb,0xbd55bd0e,0x3d3e3d2c,0xbd22bd46,0x3d043d5c,0xbcc4bd6d,0x3c793d78,0xbbc9bd7f,0xbb493d80,0x3c48bd7b,0xbcac3d71,0x3cf1bd62,0xbd183d4e,
0x3d35bd35,0xbd4e3d18,0x3d62bcf1,0xbd713cac,0x3d7bbc48,0xbd803b49,0x3d7f3bc9,0xbd78bc79,0x3d6d3cc4,0xbd5cbd04,0x3d463d22,0xbd2cbd3e,0x3d0e3d55,0xbcdbbd67,0x3c953d75,0xbc16bd7d,
0xbc48bd7b,0xbc163d7d,0x3cf1bd62,0xbd3e3d2c,0xbd800000,0x3d713cac,0xbd46bd22,0x3d043d5c,0x3d0e3d55,0xbc79bd78,0xbbc93d7f,0x3cdbbd67,0x3d6dbcc4,0xbd803b49,0x3d753c95,0xbd4ebd18,
0xbd55bd0e,0x3d183d4e,0xbc95bd75,0xbb493d80,0xbd353d35,0x3d67bcdb,0xbd7f3bc9,0x3d783c79,0x3d7b3c48,0xbd5cbd04,0x3d223d46,0xbcacbd71,0x3cc4bd6d,0xbd2c3d3e,0x3d62bcf1,0xbd7d3c16,
0x3cc43d6d,0x3c16bd7d,0xbd223d46,0x3d71bcac,0xbd7bbc48,0x3d3e3d2c,0xbc95bd75,0xbc793d78,0xbd800000,0x3d5c3d04,0xbcf1bd62,0xbb493d80,0x3d0ebd55,0xbd673cdb,0x3d7f3bc9,0xbd4ebd18,
0xbd6dbcc4,0x3d183d4e,0xbbc9bd7f,0xbcdb3d67,0x3d55bd0e,0xbd803b49,0x3d623cf1,0xbd04bd5c,0x3d35bd35,0xbd783c79,0x3d753c95,0xbd2cbd3e,0x3c483d7b,0x3cacbd71,0xbd463d22,0x3d7dbc16,
0x3d55bd0e,0xbd7dbc16,0x3d223d46,0x3b49bd80,0xbd6d3cc4,0x3d713cac,0xbcf1bd62,0xbc793d78,0x3d7bbc48,0xbd5cbd04,0x3c953d75,0x3cdbbd67,0xbd800000,0x3d3e3d2c,0xbbc9bd7f,0xbd183d4e,
0x3c48bd7b,0xbd4e3d18,0x3d7f3bc9,0xbd2cbd3e,0xbcc43d6d,0x3d67bcdb,0xbd75bc95,0x3d043d5c,0x3d0ebd55,0xbd783c79,0x3d623cf1,0xbcacbd71,0xbd353d35,0x3d80bb49,0xbd46bd22,0x3c163d7d,
0x3d35bd35,0xbd7dbc16,0x3cf13d62,0x3cdbbd67,0xbd7b3c48,0x3d3e3d2c,0x3bc9bd7f,0xbd5c3d04,0x3d6d3cc4,0xbc79bd78,0xbd223d46,0x3d803b49,0xbd0ebd55,0xbcac3d71,0x3d75bc95,0xbd4ebd18,
0xbd800000,0x3d183d4e,0x3c95bd75,0xbd713cac,0x3d553d0e,0xbb49bd80,0xbd463d22,0x3d783c79,0xbcc4bd6d,0xbd043d5c,0x3d7fbbc9,0xbd2cbd3e,0xbc483d7b,0x3d67bcdb,0xbd62bcf1,0x3c163d7d,
0x3d553d0e,0x3c16bd7d,0xbd753c95,0x3d2c3d3e,0xbd353d35,0x3d713cac,0xbbc9bd7f,0xbd5c3d04,0xbd7bbc48,0x3c793d78,0x3d46bd22,0xbd67bcdb,0x3cc4bd6d,0xbd803b49,0x3cf13d62,0x3d18bd4e,
0x3c483d7b,0x3d4ebd18,0xbd62bcf1,0xbb493d80,0xbd800000,0x3cdb3d67,0x3d22bd46,0xbd78bc79,0xbd0ebd55,0xbd043d5c,0x3d7f3bc9,0xbcacbd71,0x3d6dbcc4,0xbd3ebd2c,0xbc953d75,0x3d7dbc16,
0xbd6dbcc4,0xbc163d7d,0x3d7fbbc9,0xbcacbd71,0xbd553d0e,0x3d3e3d2c,0x3cf1bd62,0xbd78bc79,0x3d35bd35,0xbd5cbd04,0xbc953d75,0x3d803b49,0xbc48bd7b,0xbd673cdb,0x3d223d46,0x3d18bd4e,
0x3cc43d6d,0x3d4ebd18,0xbd46bd22,0xbcdb3d67,0x3d7b3c48,0xbb49bd80,0xbd753c95,0x3d043d5c,0xbd800000,0x3c793d78,0x3d62bcf1,0xbd2cbd3e,0xbd0e3d55,0x3d713cac,0x3bc9bd7f,0xbd7d3c16,
0xbc483d7b,0x3d7d3c16,0x3bc9bd7f,0xbd80bb49,0xbcc43d6d,0x3d713cac,0x3c95bd75,0xbd78bc79,0xbd0e3d55,0x3d5c3d04,0x3cf1bd62,0xbd67bcdb,0xbd353d35,0x3d3e3d2c,0x3d22bd46,0xbd4ebd18,
0xbd553d0e,0x3d183d4e,0x3d46bd22,0xbd2cbd3e,0xbd6d3cc4,0x3cdb3d67,0x3d62bcf1,0xbd04bd5c,0xbd7b3c48,0x3c793d78,0x3d75bc95,0xbcacbd71,0xbd800000,0x3b493d80,0x3d7fbbc9,0xbc16bd7d,
0x3d80,0x3d7d3c16,0x3c95bd75,0xbd67bcdb,0xbd0e3d55,0x3d3e3d2c,0x3d46bd22,0xbd04bd5c,0xbd6d3cc4,0x3c793d78,0x3d7fbbc9,0x3b49bd80,0xbd7bbc48,0xbcac3d71,0x3d623cf1,0x3d18bd4e,
0xbd35bd35,0xbd4e3d18,0x3cf13d62,0x3d71bcac,0xbc48bd7b,0xbd803b49,0xbbc93d7f,0x3d783c79,0x3cc4bd6d,0xbd5cbd04,0xbd223d46,0x3d2c3d3e,0x3d55bd0e,0xbcdbbd67,0xbd753c95,0x3c163d7d,
0xbd7b3c48,0xbc163d7d,0x3d623cf1,0x3d3ebd2c,0x3d80,0x3d713cac,0x3d22bd46,0xbd04bd5c,0x3d55bd0e,0xbc79bd78,0xbd7fbbc9,0xbcdb3d67,0xbcc4bd6d,0xbd803b49,0xbc953d75,0x3d4e3d18,
0xbd0e3d55,0x3d183d4e,0x3d75bc95,0x3b49bd80,0x3d353d35,0x3d67bcdb,0xbbc9bd7f,0xbd78bc79,0x3c48bd7b,0xbd5cbd04,0xbd463d22,0x3cac3d71,0xbd6dbcc4,0xbd2c3d3e,0x3cf13d62,0x3d7dbc16,
0x3d6dbcc4,0x3c16bd7d,0xbd46bd22,0xbd713cac,0xbc483d7b,0x3d3e3d2c,0x3d75bc95,0x3c79bd78,0x3d80,0x3d5c3d04,0x3d62bcf1,0x3b49bd80,0xbd55bd0e,0xbd673cdb,0xbbc93d7f,0x3d4e3d18,
0xbcc43d6d,0x3d183d4e,0x3d7fbbc9,0x3cdbbd67,0xbd0ebd55,0xbd803b49,0xbcf13d62,0x3d043d5c,0xbd35bd35,0xbd783c79,0xbc953d75,0x3d2c3d3e,0x3d7bbc48,0x3cacbd71,0xbd22bd46,0xbd7d3c16,
0xbd0ebd55,0xbd7dbc16,0xbd463d22,0xbb493d80,0x3cc43d6d,0x3d713cac,0x3d62bcf1,0x3c79bd78,0xbc48bd7b,0xbd5cbd04,0xbd753c95,0xbcdb3d67,0x3d80,0x3d3e3d2c,0x3d7fbbc9,0x3d18bd4e,
0xbd7bbc48,0xbd4e3d18,0xbbc93d7f,0x3d2c3d3e,0x3d6d3cc4,0x3d67bcdb,0x3c95bd75,0xbd04bd5c,0xbd55bd0e,0xbd783c79,0xbcf13d62,0x3cac3d71,0x3d353d35,0x3d80bb49,0x3d22bd46,0xbc16bd7d,
0xbd35bd35,0xbd7dbc16,0xbd623cf1,0xbcdb3d67,0x3c483d7b,0x3d3e3d2c,0x3d7f3bc9,0x3d5cbd04,0x3cc4bd6d,0xbc79bd78,0xbd46bd22,0xbd80bb49,0xbd553d0e,0xbcac3d71,0x3c953d75,0x3d4e3d18,
0x3d80,0x3d183d4e,0x3d753c95,0x3d71bcac,0x3d0ebd55,0xbb49bd80,0xbd22bd46,0xbd78bc79,0xbd6d3cc4,0xbd043d5c,0x3bc93d7f,0x3d2c3d3e,0x3d7b3c48,0x3d67bcdb,0x3cf1bd62,0xbc16bd7d,
0x3d0ebd55,0x3c16bd7d,0xbc95bd75,0xbd2cbd3e,0x3d353d35,0x3d713cac,0x3d7fbbc9,0x3d5cbd04,0xbc483d7b,0x3c793d78,0x3d223d46,0x3d673cdb,0xbd6dbcc4,0xbd803b49,0xbd623cf1,0xbd183d4e,
0x3d7bbc48,0x3d4ebd18,0x3cf1bd62,0x3b49bd80,0x3d80,0x3cdb3d67,0x3d463d22,0x3d783c79,0xbd553d0e,0xbd043d5c,0xbbc93d7f,0x3cac3d71,0xbcc4bd6d,0xbd3ebd2c,0xbd75bc95,0xbd7d3c16,
0xbcc43d6d,0xbc163d7d,0x3bc93d7f,0x3cac3d71,0x3d0e3d55,0x3d3e3d2c,0x3d623cf1,0x3d783c79,0xbd35bd35,0xbd5cbd04,0xbd75bc95,0xbd80bb49,0xbd7b3c48,0xbd673cdb,0xbd463d22,0xbd183d4e,
0x3d6dbcc4,0x3d4ebd18,0x3d22bd46,0x3cdbbd67,0x3c48bd7b,0xbb49bd80,0xbc95bd75,0xbd04bd5c,0x3d80,0x3c793d78,0x3cf13d62,0x3d2c3d3e,0x3d553d0e,0x3d713cac,0x3d7f3bc9,0x3d7dbc16,
0x3d7b3c48,0x3d7d3c16,0x3d7f3bc9,0x3d803b49,0x3d6d3cc4,0x3d713cac,0x3d753c95,0x3d783c79,0x3d553d0e,0x3d5c3d04,0x3d623cf1,0x3d673cdb,0x3d353d35,0x3d3e3d2c,0x3d463d22,0x3d4e3d18,
0x3d0e3d55,0x3d183d4e,0x3d223d46,0x3d2c3d3e,0x3cc43d6d,0x3cdb3d67,0x3cf13d62,0x3d043d5c,0x3c483d7b,0x3c793d78,0x3c953d75,0x3cac3d71,0x3d80,0x3b493d80,0x3bc93d7f,0x3c163d7d,
0xbd800000,0xbc163d7d,0x3d753c95,0x3cdbbd67,0xbd55bd0e,0xbd2c3d3e,0x3d223d46,0x3d5cbd04,0xbcc4bd6d,0xbd783c79,0x3bc93d7f,0x3d803b49,0x3c48bd7b,0xbd71bcac,0xbcf13d62,0x3d4e3d18,
0x3d35bd35,0xbd18bd4e,0xbd623cf1,0x3cac3d71,0x3d7bbc48,0xbb49bd80,0xbd7fbbc9,0xbc793d78,0x3d6d3cc4,0x3d04bd5c,0xbd46bd22,0xbd3e3d2c,0x3d0e3d55,0x3d67bcdb,0xbc95bd75,0xbd7d3c16,
0xbc48bd7b,0xbd7dbc16,0xbcf13d62,0x3d2c3d3e,0xbd800000,0xbcac3d71,0x3d463d22,0x3d5cbd04,0x3d0e3d55,0x3d78bc79,0x3bc9bd7f,0xbd67bcdb,0x3d6dbcc4,0xbb49bd80,0xbd75bc95,0xbd183d4e,
0xbd55bd0e,0xbd4e3d18,0x3c953d75,0x3d803b49,0xbd353d35,0x3cdb3d67,0x3d7fbbc9,0x3c79bd78,0x3d7b3c48,0x3d04bd5c,0xbd22bd46,0xbd713cac,0x3cc4bd6d,0xbd3ebd2c,0xbd623cf1,0x3c163d7d,
0x3cc43d6d,0x3d7d3c16,0x3d22bd46,0xbcacbd71,0xbd7bbc48,0xbd2c3d3e,0x3c953d75,0x3d783c79,0xbd800000,0xbd043d5c,0x3cf13d62,0x3d803b49,0x3d0ebd55,0xbcdbbd67,0xbd7fbbc9,0xbd183d4e,
0xbd6dbcc4,0xbd4e3d18,0x3bc93d7f,0x3d673cdb,0x3d55bd0e,0xbb49bd80,0xbd62bcf1,0xbd5c3d04,0x3d35bd35,0xbc79bd78,0xbd75bc95,0xbd3e3d2c,0x3c483d7b,0x3d713cac,0x3d46bd22,0xbc16bd7d,
0x3d55bd0e,0x3c16bd7d,0xbd22bd46,0xbd80bb49,0xbd6d3cc4,0xbcac3d71,0x3cf13d62,0x3d783c79,0x3d7bbc48,0x3d04bd5c,0xbc95bd75,0xbd67bcdb,0xbd800000,0xbd2c3d3e,0x3bc93d7f,0x3d4e3d18,
0x3c48bd7b,0xbd18bd4e,0xbd7fbbc9,0xbd3e3d2c,0xbcc43d6d,0x3cdb3d67,0x3d753c95,0x3d5cbd04,0x3d0ebd55,0xbc79bd78,0xbd62bcf1,0xbd713cac,0xbd353d35,0x3b493d80,0x3d463d22,0x3d7dbc16,
0x3d35bd35,0x3c16bd7d,0xbcf1bd62,0xbd67bcdb,0xbd7b3c48,0xbd2c3d3e,0xbbc93d7f,0x3d043d5c,0x3d6d3cc4,0x3d78bc79,0x3d22bd46,0x3b49bd80,0xbd0ebd55,0xbd71bcac,0xbd753c95,0xbd183d4e,
0xbd800000,0xbd4e3d18,0xbc953d75,0x3cac3d71,0x3d553d0e,0x3d80bb49,0x3d46bd22,0x3c79bd78,0xbcc4bd6d,0xbd5cbd04,0xbd7f3bc9,0xbd3e3d2c,0xbc483d7b,0x3cdb3d67,0x3d623cf1,0x3d7dbc16,
0x3d553d0e,0x3d7d3c16,0x3d75bc95,0x3d3ebd2c,0xbd353d35,0xbcac3d71,0x3bc93d7f,0x3d043d5c,0xbd7bbc48,0xbd783c79,0xbd463d22,0xbcdb3d67,0x3cc4bd6d,0xbb49bd80,0xbcf1bd62,0xbd4ebd18,
0x3c483d7b,0x3d183d4e,0x3d623cf1,0x3d803b49,0xbd800000,0xbd673cdb,0xbd223d46,0xbc793d78,0xbd0ebd55,0xbd5cbd04,0xbd7fbbc9,0xbd713cac,0x3d6dbcc4,0x3d2cbd3e,0x3c95bd75,0xbc16bd7d,
0xbd6dbcc4,0xbd7dbc16,0xbd7f3bc9,0xbd713cac,0xbd553d0e,0xbd2c3d3e,0xbcf13d62,0xbc793d78,0x3d35bd35,0x3d04bd5c,0x3c95bd75,0x3b49bd80,0xbc48bd7b,0xbcdbbd67,0xbd22bd46,0xbd4ebd18,
0x3cc43d6d,0x3d183d4e,0x3d463d22,0x3d673cdb,0x3d7b3c48,0x3d80bb49,0x3d75bc95,0x3d5cbd04,0xbd800000,0xbd783c79,0xbd623cf1,0xbd3e3d2c,0xbd0e3d55,0xbcac3d71,0xbbc93d7f,0x3c163d7d,
0xbc483d7b,0xbc163d7d,0xbbc93d7f,0xbb493d80,0xbcc43d6d,0xbcac3d71,0xbc953d75,0xbc793d78,0xbd0e3d55,0xbd043d5c,0xbcf13d62,0xbcdb3d67,0xbd353d35,0xbd2c3d3e,0xbd223d46,0xbd183d4e,
0xbd553d0e,0xbd4e3d18,0xbd463d22,0xbd3e3d2c,0xbd6d3cc4,0xbd673cdb,0xbd623cf1,0xbd5c3d04,0xbd7b3c48,0xbd783c79,0xbd753c95,0xbd713cac,0xbd800000,0xbd803b49,0xbd7f3bc9,0xbd7d3c16,
0x3f003f00,0xbf003f00,0x3f003f00,0xbf003f00,0x3f003f00,0xbf003f00,0x3f003f00,0xbf003f00,0x3f003f00,0xbf003f00,0x3f003f00,0xbf003f00,0x3f003f00,0xbf003f00,0x3f003f00,0xbf003f00,
0x3eff3f00,0xbd490000,0x3ea23eb5,0xbec6beb5,0x3ef53efb,0xbe15bdc8,0x3e713e8e,0xbee2bed5,0x3ee23eed,0xbe71be44,0x3e153e44,0xbef5beed,0x3ec63ed5,0xbea2be8e,0x3d493dc8,0xbeffbefb,
0x3efb3f00,0xbdc80000,0xbdc80000,0xbefbbf00,0x3ed53eed,0xbe8ebe44,0xbe8ebe44,0xbed5beed,0x3e8e3eb5,0xbed5beb5,0xbed5beb5,0xbe8ebeb5,0x3dc83e44,0xbefbbeed,0xbefbbeed,0xbdc8be44,
0x3ef53f00,0xbe150000,0xbee2beb5,0xbe71beb5,0x3ea23ed5,0xbec6be8e,0xbeffbefb,0x3d49bdc8,0x3d493e44,0xbeffbeed,0xbec6beed,0x3ea23e44,0xbe71bdc8,0xbee2befb,0xbe15be8e,0x3ef53ed5,
0x3eed3f00,0xbe440000,0xbeedbf00,0x3e440000,0x3e443eb5,0xbeedbeb5,0xbe44beb5,0x3eed3eb5,0xbe440000,0xbeedbf00,0x3e440000,0x3eed3f00,0xbeedbeb5,0xbe44beb5,0x3eed3eb5,0x3e443eb5,
0x3ee23f00,0xbe710000,0xbe15beb5,0x3ef53eb5,0x3d493e8e,0xbeffbed5,0x3ea23dc8,0x3ec63efb,0xbec6be44,0xbea2beed,0x3eff3eed,0xbd493e44,0xbef5befb,0x3e15bdc8,0x3e713ed5,0xbee2be8e,
0x3ed53f00,0xbe8e0000,0x3e8e0000,0x3ed53f00,0xbdc83e44,0xbefbbeed,0x3efb3eed,0xbdc83e44,0xbefbbeb5,0xbdc8beb5,0x3dc83eb5,0xbefbbeb5,0xbe8ebeed,0x3ed53e44,0xbed5be44,0xbe8ebeed,
0x3ec63f00,0xbea20000,0x3eff3eb5,0x3d493eb5,0xbe713dc8,0xbee2befb,0x3e153ed5,0xbef5be8e,0xbef5beed,0x3e15be44,0xbee2be44,0xbe71beed,0x3d49be8e,0x3eff3ed5,0xbea2befb,0x3ec63dc8,
0x3f00,0xbf000000,0x3f00,0xbf000000,0xbf00,0x3f000000,0xbf00,0x3f000000,0x3f00,0xbf000000,0x3f00,0xbf000000,0xbf00,0x3f000000,0xbf00,0x3f000000,
0xbd493f00,0xbeff0000,0xbec63eb5,0xbea2beb5,0x3e15befb,0x3ef53dc8,0x3ee2be8e,0x3e713ed5,0xbe713eed,0xbee2be44,0xbef53e44,0xbe15beed,0x3ea2bed5,0x3ec63e8e,0x3effbdc8,0x3d493efb,
0xbdc83f00,0xbefb0000,0xbefb0000,0x3dc8bf00,0x3e8ebeed,0x3ed53e44,0x3ed53e44,0xbe8e3eed,0xbed53eb5,0xbe8ebeb5,0xbe8ebeb5,0x3ed5beb5,0x3efbbe44,0x3dc83eed,0x3dc83eed,0xbefb3e44,
0xbe153f00,0xbef50000,0xbe71beb5,0x3ee2beb5,0x3ec6bed5,0x3ea23e8e,0xbd493efb,0xbeff3dc8,0xbeff3e44,0xbd49beed,0x3ea2beed,0x3ec63e44,0x3ee23dc8,0xbe713efb,0xbef53e8e,0xbe15bed5,
0xbe443f00,0xbeed0000,0x3e44bf00,0x3eed0000,0x3eedbeb5,0x3e443eb5,0xbeed3eb5,0xbe44beb5,0xbeed0000,0x3e44bf00,0x3eed0000,0xbe443f00,0x3e443eb5,0xbeed3eb5,0xbe44beb5,0x3eedbeb5,
0xbe713f00,0xbee20000,0x3ef5beb5,0x3e153eb5,0x3effbe8e,0x3d493ed5,0xbec6bdc8,0x3ea2befb,0xbea2be44,0x3ec6beed,0xbd493eed,0xbeff3e44,0xbe153efb,0xbef53dc8,0x3ee2bed5,0x3e713e8e,
0xbe8e3f00,0xbed50000,0x3ed50000,0xbe8e3f00,0x3efbbe44,0xbdc83eed,0x3dc8beed,0x3efbbe44,0xbdc8beb5,0x3efbbeb5,0xbefb3eb5,0xbdc8beb5,0xbed53eed,0xbe8ebe44,0x3e8e3e44,0xbed53eed,
0xbea23f00,0xbec60000,0x3d493eb5,0xbeff3eb5,0x3ee2bdc8,0xbe713efb,0x3ef5bed5,0x3e153e8e,0x3e15beed,0x3ef5be44,0xbe71be44,0x3ee2beed,0xbeff3e8e,0x3d49bed5,0xbec63efb,0xbea2bdc8,
0x3eb53f00,0xbeb50000,0x3eb53f00,0xbeb50000,0xbeb50000,0xbeb5bf00,0xbeb50000,0xbeb5bf00,0xbeb5bf00,0x3eb50000,0xbeb5bf00,0x3eb50000,0x3eb50000,0x3eb53f00,0x3eb50000,0x3eb53f00,
0xbeff3f00,0x3d490000,0xbea23eb5,0x3ec6beb5,0xbef53efb,0x3e15bdc8,0xbe713e8e,0x3ee2bed5,0xbee23eed,0x3e71be44,0xbe153e44,0x3ef5beed,0xbec63ed5,0x3ea2be8e,0xbd493dc8,0x3effbefb,
0xbefb3f00,0x3dc80000,0x3dc80000,0x3efbbf00,0xbed53eed,0x3e8ebe44,0x3e8ebe44,0x3ed5beed,0xbe8e3eb5,0x3ed5beb5,0x3ed5beb5,0x3e8ebeb5,0xbdc83e44,0x3efbbeed,0x3efbbeed,0x3dc8be44,
0xbef53f00,0x3e150000,0x3ee2beb5,0x3e71beb5,0xbea23ed5,0x3ec6be8e,0x3effbefb,0xbd49bdc8,0xbd493e44,0x3effbeed,0x3ec6beed,0xbea23e44,0x3e71bdc8,0x3ee2befb,0x3e15be8e,0xbef53ed5,
0xbeed3f00,0x3e440000,0x3eedbf00,0xbe440000,0xbe443eb5,0x3eedbeb5,0x3e44beb5,0xbeed3eb5,0x3e440000,0x3eedbf00,0xbe440000,0xbeed3f00,0x3eedbeb5,0x3e44beb5,0xbeed3eb5,0xbe443eb5,
0xbee23f00,0x3e710000,0x3e15beb5,0xbef53eb5,0xbd493e8e,0x3effbed5,0xbea23dc8,0xbec63efb,0x3ec6be44,0x3ea2beed,0xbeff3eed,0x3d493e44,0x3ef5befb,0xbe15bdc8,0xbe713ed5,0x3ee2be8e,
0xbed53f00,0x3e8e0000,0xbe8e0000,0xbed53f00,0x3dc83e44,0x3efbbeed,0xbefb3eed,0x3dc83e44,0x3efbbeb5,0x3dc8beb5,0xbdc83eb5,0x3efbbeb5,0x3e8ebeed,0xbed53e44,0x3ed5be44,0x3e8ebeed,
0xbec63f00,0x3ea20000,0xbeff3eb5,0xbd493eb5,0x3e713dc8,0x3ee2befb,0xbe153ed5,0x3ef5be8e,0x3ef5beed,0xbe15be44,0x3ee2be44,0x3e71beed,0xbd49be8e,0xbeff3ed5,0x3ea2befb,0xbec63dc8,
0xbeb53f00,0xbeb50000,0xbeb53f00,0xbeb50000,0x3eb50000,0xbeb53f00,0x3eb50000,0xbeb53f00,0x3eb5bf00,0x3eb50000,0x3eb5bf00,0x3eb50000,0xbeb50000,0x3eb5bf00,0xbeb50000,0x3eb5bf00,
0x3d493f00,0x3eff0000,0x3ec63eb5,0x3ea2beb5,0xbe15befb,0xbef53dc8,0xbee2be8e,0xbe713ed5,0x3e713eed,0x3ee2be44,0x3ef53e44,0x3e15beed,0xbea2bed5,0xbec63e8e,0xbeffbdc8,0xbd493efb,
0x3dc83f00,0x3efb0000,0x3efb0000,0xbdc8bf00,0xbe8ebeed,0xbed53e44,0xbed53e44,0x3e8e3eed,0x3ed53eb5,0x3e8ebeb5,0x3e8ebeb5,0xbed5beb5,0xbefbbe44,0xbdc83eed,0xbdc83eed,0x3efb3e44,
0x3e153f00,0x3ef50000,0x3e71beb5,0xbee2beb5,0xbec6bed5,0xbea23e8e,0x3d493efb,0x3eff3dc8,0x3eff3e44,0x3d49beed,0xbea2beed,0xbec63e44,0xbee23dc8,0x3e713efb,0x3ef53e8e,0x3e15bed5,
0x3e443f00,0x3eed0000,0xbe44bf00,0xbeed0000,0xbeedbeb5,0xbe443eb5,0x3eed3eb5,0x3e44beb5,0x3eed0000,0xbe44bf00,0xbeed0000,0x3e443f00,0xbe443eb5,0x3eed3eb5,0x3e44beb5,0xbeedbeb5,
0x3e713f00,0x3ee20000,0xbef5beb5,0xbe153eb5,0xbeffbe8e,0xbd493ed5,0x3ec6bdc8,0xbea2befb,0x3ea2be44,0xbec6beed,0x3d493eed,0x3eff3e44,0x3e153efb,0x3ef53dc8,0xbee2bed5,0xbe713e8e,
0x3e8e3f00,0x3ed50000,0xbed50000,0x3e8e3f00,0xbefbbe44,0x3dc83eed,0xbdc8beed,0xbefbbe44,0x3dc8beb5,0xbefbbeb5,0x3efb3eb5,0x3dc8beb5,0x3ed53eed,0x3e8ebe44,0xbe8e3e44,0x3ed53eed,
0x3ea23f00,0x3ec60000,0xbd493eb5,0x3eff3eb5,0xbee2bdc8,0x3e713efb,0xbef5bed5,0xbe153e8e,0xbe15beed,0xbef5be44,0x3e71be44,0xbee2beed,0x3eff3e8e,0xbd49bed5,0x3ec63efb,0x3ea2bdc8,
0x3f003f00,0xbf003f00,0x3f003f00,0xbf003f00,0x3f003f00,0xbf003f00,0x3f003f00,0xbf003f00,0x3f003f00,0xbf003f00,0x3f003f00,0xbf003f00,0x3f003f00,0xbf003f00,0x3f003f00,0xbf003f00,
0xbd490000,0xbeffbf00,0xbec6beb5,0xbea2beb5,0xbe15bdc8,0xbef5befb,0xbee2bed5,0xbe71be8e,0xbe71be44,0xbee2beed,0xbef5beed,0xbe15be44,0xbea2be8e,0xbec6bed5,0xbeffbefb,0xbd49bdc8,
0xbefbbf00,0x3dc80000,0x3dc80000,0x3efb3f00,0xbed5beed,0x3e8e3e44,0x3e8e3e44,0x3ed53eed,0xbe8ebeb5,0x3ed53eb5,0x3ed53eb5,0x3e8e3eb5,0xbdc8be44,0x3efb3eed,0x3efb3eed,0x3dc83e44,
0x3e150000,0x3ef53f00,0x3e713eb5,0xbee2beb5,0x3ec63e8e,0x3ea23ed5,0xbd493dc8,0xbeffbefb,0x3eff3eed,0x3d493e44,0xbea2be44,0xbec6beed,0x3ee23efb,0xbe71bdc8,0xbef5bed5,0xbe15be8e,
0x3eed3f00,0xbe440000,0xbeedbf00,0x3e440000,0x3e443eb5,0xbeedbeb5,0xbe44beb5,0x3eed3eb5,0xbe440000,0xbeedbf00,0x3e440000,0x3eed3f00,0xbeedbeb5,0xbe44beb5,0x3eed3eb5,0x3e443eb5,
0xbe710000,0xbee2bf00,0x3ef53eb5,0x3e153eb5,0xbeffbed5,0xbd49be8e,0x3ec63efb,0xbea2bdc8,0xbea2beed,0x3ec63e44,0xbd493e44,0xbeffbeed,0x3e15bdc8,0x3ef53efb,0xbee2be8e,0xbe71bed5,
0xbed5bf00,0x3e8e0000,0xbe8e0000,0xbed5bf00,0x3dc8be44,0x3efb3eed,0xbefbbeed,0x3dc8be44,0x3efb3eb5,0x3dc83eb5,0xbdc8beb5,0x3efb3eb5,0x3e8e3eed,0xbed5be44,0x3ed53e44,0x3e8e3eed,
0x3ea20000,0x3ec63f00,0xbd49beb5,0x3eff3eb5,0x3ee23efb,0xbe713dc8,0x3ef53e8e,0x3e153ed5,0xbe153e44,0xbef5beed,0x3e713eed,0xbee2be44,0xbeffbed5,0x3d49be8e,0xbec6bdc8,0xbea2befb,
0x3f00,0xbf000000,0x3f00,0xbf000000,0xbf00,0x3f000000,0xbf00,0x3f000000,0x3f00,0xbf000000,0x3f00,0xbf000000,0xbf00,0x3f000000,0xbf00,0x3f000000,
0xbeff0000,0x3d49bf00,0xbea2beb5,0x3ec6beb5,0x3ef53dc8,0xbe153efb,0x3e713ed5,0xbee23e8e,0xbee2be44,0x3e71beed,0xbe15beed,0x3ef5be44,0x3ec63e8e,0xbea23ed5,0x3d493efb,0xbeff3dc8,
0x3dc8bf00,0x3efb0000,0x3efb0000,0xbdc83f00,0xbe8e3eed,0xbed5be44,0xbed5be44,0x3e8ebeed,0x3ed5beb5,0x3e8e3eb5,0x3e8e3eb5,0xbed53eb5,0xbefb3e44,0xbdc8beed,0xbdc8beed,0x3efbbe44,
0x3ef50000,0xbe153f00,0xbee23eb5,0xbe71beb5,0xbea2be8e,0x3ec6bed5,0x3effbdc8,0xbd493efb,0x3d493eed,0xbeff3e44,0xbec6be44,0x3ea2beed,0x3e71befb,0x3ee23dc8,0x3e153ed5,0xbef53e8e,
0xbe443f00,0xbeed0000,0x3e44bf00,0x3eed0000,0x3eedbeb5,0x3e443eb5,0xbeed3eb5,0xbe44beb5,0xbeed0000,0x3e44bf00,0x3eed0000,0xbe443f00,0x3e443eb5,0xbeed3eb5,0xbe44beb5,0x3eedbeb5,
0xbee20000,0x3e71bf00,0x3e153eb5,0xbef53eb5,0x3d493ed5,0xbeff3e8e,0x3ea2befb,0x3ec63dc8,0x3ec6beed,0x3ea23e44,0xbeff3e44,0x3d49beed,0xbef53dc8,0x3e15befb,0x3e713e8e,0xbee23ed5,
0x3e8ebf00,0x3ed50000,0xbed50000,0x3e8ebf00,0xbefb3e44,0x3dc8beed,0xbdc83eed,0xbefb3e44,0x3dc83eb5,0xbefb3eb5,0x3efbbeb5,0x3dc83eb5,0x3ed5beed,0x3e8e3e44,0xbe8ebe44,0x3ed5beed,
0x3ec60000,0xbea23f00,0x3effbeb5,0x3d493eb5,0x3e71befb,0x3ee2bdc8,0xbe15be8e,0x3ef5bed5,0xbef53e44,0x3e15beed,0xbee23eed,0xbe71be44,0xbd493ed5,0xbeff3e8e,0x3ea23dc8,0xbec63efb,
0x3eb53f00,0xbeb50000,0x3eb53f00,0xbeb50000,0xbeb50000,0xbeb5bf00,0xbeb50000,0xbeb5bf00,0xbeb5bf00,0x3eb50000,0xbeb5bf00,0x3eb50000,0x3eb50000,0x3eb53f00,0x3eb50000,0x3eb53f00,
0x3d490000,0x3effbf00,0x3ec6beb5,0x3ea2beb5,0x3e15bdc8,0x3ef5befb,0x3ee2bed5,0x3e71be8e,0x3e71be44,0x3ee2beed,0x3ef5beed,0x3e15be44,0x3ea2be8e,0x3ec6bed5,0x3effbefb,0x3d49bdc8,
0x3efbbf00,0xbdc80000,0xbdc80000,0xbefb3f00,0x3ed5beed,0xbe8e3e44,0xbe8e3e44,0xbed53eed,0x3e8ebeb5,0xbed53eb5,0xbed53eb5,0xbe8e3eb5,0x3dc8be44,0xbefb3eed,0xbefb3eed,0xbdc83e44,
0xbe150000,0xbef53f00,0xbe713eb5,0x3ee2beb5,0xbec63e8e,0xbea23ed5,0x3d493dc8,0x3effbefb,0xbeff3eed,0xbd493e44,0x3ea2be44,0x3ec6beed,0xbee23efb,0x3e71bdc8,0x3ef5bed5,0x3e15be8e,
0xbeed3f00,0x3e440000,0x3eedbf00,0xbe440000,0xbe443eb5,0x3eedbeb5,0x3e44beb5,0xbeed3eb5,0x3e440000,0x3eedbf00,0xbe440000,0xbeed3f00,0x3eedbeb5,0x3e44beb5,0xbeed3eb5,0xbe443eb5,
0x3e710000,0x3ee2bf00,0xbef53eb5,0xbe153eb5,0x3effbed5,0x3d49be8e,0xbec63efb,0x3ea2bdc8,0x3ea2beed,0xbec63e44,0x3d493e44,0x3effbeed,0xbe15bdc8,0xbef53efb,0x3ee2be8e,0x3e71bed5,
0x3ed5bf00,0xbe8e0000,0x3e8e0000,0x3ed5bf00,0xbdc8be44,0xbefb3eed,0x3efbbeed,0xbdc8be44,0xbefb3eb5,0xbdc83eb5,0x3dc8beb5,0xbefb3eb5,0xbe8e3eed,0x3ed5be44,0xbed53e44,0xbe8e3eed,
0xbea20000,0xbec63f00,0x3d49beb5,0xbeff3eb5,0xbee23efb,0x3e713dc8,0xbef53e8e,0xbe153ed5,0x3e153e44,0x3ef5beed,0xbe713eed,0x3ee2be44,0x3effbed5,0xbd49be8e,0x3ec6bdc8,0x3ea2befb,
0xbeb53f00,0xbeb50000,0xbeb53f00,0xbeb50000,0x3eb50000,0xbeb53f00,0x3eb50000,0xbeb53f00,0x3eb5bf00,0x3eb50000,0x3eb5bf00,0x3eb50000,0xbeb50000,0x3eb5bf00,0xbeb50000,0x3eb5bf00,
0x3eff0000,0xbd49bf00,0x3ea2beb5,0xbec6beb5,0xbef53dc8,0x3e153efb,0xbe713ed5,0x3ee23e8e,0x3ee2be44,0xbe71beed,0x3e15beed,0xbef5be44,0xbec63e8e,0x3ea23ed5,0xbd493efb,0x3eff3dc8,
0xbdc8bf00,0xbefb0000,0xbefb0000,0x3dc83f00,0x3e8e3eed,0x3ed5be44,0x3ed5be44,0xbe8ebeed,0xbed5beb5,0xbe8e3eb5,0xbe8e3eb5,0x3ed53eb5,0x3efb3e44,0x3dc8beed,0x3dc8beed,0xbefbbe44,
0xbef50000,0x3e153f00,0x3ee23eb5,0x3e71beb5,0x3ea2be8e,0xbec6bed5,0xbeffbdc8,0x3d493efb,0xbd493eed,0x3eff3e44,0x3ec6be44,0xbea2beed,0xbe71befb,0xbee23dc8,0xbe153ed5,0x3ef53e8e,
0x3e443f00,0x3eed0000,0xbe44bf00,0xbeed0000,0xbeedbeb5,0xbe443eb5,0x3eed3eb5,0x3e44beb5,0x3eed0000,0xbe44bf00,0xbeed0000,0x3e443f00,0xbe443eb5,0x3eed3eb5,0x3e44beb5,0xbeedbeb5,
0x3ee20000,0xbe71bf00,0xbe153eb5,0x3ef53eb5,0xbd493ed5,0x3eff3e8e,0xbea2befb,0xbec63dc8,0xbec6beed,0xbea23e44,0x3eff3e44,0xbd49beed,0x3ef53dc8,0xbe15befb,0xbe713e8e,0x3ee23ed5,
0xbe8ebf00,0xbed50000,0x3ed50000,0xbe8ebf00,0x3efb3e44,0xbdc8beed,0x3dc83eed,0x3efb3e44,0xbdc83eb5,0x3efb3eb5,0xbefbbeb5,0xbdc83eb5,0xbed5beed,0xbe8e3e44,0x3e8ebe44,0xbed5beed,
0xbec60000,0x3ea23f00,0xbeffbeb5,0xbd493eb5,0xbe71befb,0xbee2bdc8,0x3e15be8e,0xbef5bed5,0x3ef53e44,0xbe15beed,0x3ee23eed,0x3e71be44,0x3d493ed5,0x3eff3e8e,0xbea23dc8,0x3ec63efb,
0x3f003f00,0xbf003f00,0x3f003f00,0xbf003f00,0x3f003f00,0xbf003f00,0x3f003f00,0xbf003f00,0x3f003f00,0xbf003f00,0x3f003f00,0xbf003f00,0x3f003f00,0xbf003f00,0x3f003f00,0xbf003f00,
0xbeffbf00,0x3d490000,0xbea2beb5,0x3ec63eb5,0xbef5befb,0x3e153dc8,0xbe71be8e,0x3ee23ed5,0xbee2beed,0x3e713e44,0xbe15be44,0x3ef53eed,0xbec6bed5,0x3ea23e8e,0xbd49bdc8,0x3eff3efb,
0x3efb3f00,0xbdc80000,0xbdc80000,0xbefbbf00,0x3ed53eed,0xbe8ebe44,0xbe8ebe44,0xbed5beed,0x3e8e3eb5,0xbed5beb5,0xbed5beb5,0xbe8ebeb5,0x3dc83e44,0xbefbbeed,0xbefbbeed,0xbdc8be44,
0xbef5bf00,0x3e150000,0x3ee23eb5,0x3e713eb5,0xbea2bed5,0x3ec63e8e,0x3eff3efb,0xbd493dc8,0xbd49be44,0x3eff3eed,0x3ec63eed,0xbea2be44,0x3e713dc8,0x3ee23efb,0x3e153e8e,0xbef5bed5,
0x3eed3f00,0xbe440000,0xbeedbf00,0x3e440000,0x3e443eb5,0xbeedbeb5,0xbe44beb5,0x3eed3eb5,0xbe440000,0xbeedbf00,0x3e440000,0x3eed3f00,0xbeedbeb5,0xbe44beb5,0x3eed3eb5,0x3e443eb5,
0xbee2bf00,0x3e710000,0x3e153eb5,0xbef5beb5,0xbd49be8e,0x3eff3ed5,0xbea2bdc8,0xbec6befb,0x3ec63e44,0x3ea23eed,0xbeffbeed,0x3d49be44,0x3ef53efb,0xbe153dc8,0xbe71bed5,0x3ee23e8e,
0x3ed53f00,0xbe8e0000,0x3e8e0000,0x3ed53f00,0xbdc83e44,0xbefbbeed,0x3efb3eed,0xbdc83e44,0xbefbbeb5,0xbdc8beb5,0x3dc83eb5,0xbefbbeb5,0xbe8ebeed,0x3ed53e44,0xbed5be44,0xbe8ebeed,
0xbec6bf00,0x3ea20000,0xbeffbeb5,0xbd49beb5,0x3e71bdc8,0x3ee23efb,0xbe15bed5,0x3ef53e8e,0x3ef53eed,0xbe153e44,0x3ee23e44,0x3e713eed,0xbd493e8e,0xbeffbed5,0x3ea23efb,0xbec6bdc8,
0x3f00,0xbf000000,0x3f00,0xbf000000,0xbf00,0x3f000000,0xbf00,0x3f000000,0x3f00,0xbf000000,0x3f00,0xbf000000,0xbf00,0x3f000000,0xbf00,0x3f000000,
0x3d49bf00,0x3eff0000,0x3ec6beb5,0x3ea23eb5,0xbe153efb,0xbef5bdc8,0xbee23e8e,0xbe71bed5,0x3e71beed,0x3ee23e44,0x3ef5be44,0x3e153eed,0xbea23ed5,0xbec6be8e,0xbeff3dc8,0xbd49befb,
0xbdc83f00,0xbefb0000,0xbefb0000,0x3dc8bf00,0x3e8ebeed,0x3ed53e44,0x3ed53e44,0xbe8e3eed,0xbed53eb5,0xbe8ebeb5,0xbe8ebeb5,0x3ed5beb5,0x3efbbe44,0x3dc83eed,0x3dc83eed,0xbefb3e44,
0x3e15bf00,0x3ef50000,0x3e713eb5,0xbee23eb5,0xbec63ed5,0xbea2be8e,0x3d49befb,0x3effbdc8,0x3effbe44,0x3d493eed,0xbea23eed,0xbec6be44,0xbee2bdc8,0x3e71befb,0x3ef5be8e,0x3e153ed5,
0xbe443f00,0xbeed0000,0x3e44bf00,0x3eed0000,0x3eedbeb5,0x3e443eb5,0xbeed3eb5,0xbe44beb5,0xbeed0000,0x3e44bf00,0x3eed0000,0xbe443f00,0x3e443eb5,0xbeed3eb5,0xbe44beb5,0x3eedbeb5,
0x3e71bf00,0x3ee20000,0xbef53eb5,0xbe15beb5,0xbeff3e8e,0xbd49bed5,0x3ec63dc8,0xbea23efb,0x3ea23e44,0xbec63eed,0x3d49beed,0x3effbe44,0x3e15befb,0x3ef5bdc8,0xbee23ed5,0xbe71be8e,
0xbe8e3f00,0xbed50000,0x3ed50000,0xbe8e3f00,0x3efbbe44,0xbdc83eed,0x3dc8beed,0x3efbbe44,0xbdc8beb5,0x3efbbeb5,0xbefb3eb5,0xbdc8beb5,0xbed53eed,0xbe8ebe44,0x3e8e3e44,0xbed53eed,
0x3ea2bf00,0x3ec60000,0xbd49beb5,0x3effbeb5,0xbee23dc8,0x3e71befb,0xbef53ed5,0xbe15be8e,0xbe153eed,0xbef53e44,0x3e713e44,0xbee23eed,0x3effbe8e,0xbd493ed5,0x3ec6befb,0x3ea23dc8,
0x3eb53f00,0xbeb50000,0x3eb53f00,0xbeb50000,0xbeb50000,0xbeb5bf00,0xbeb50000,0xbeb5bf00,0xbeb5bf00,0x3eb50000,0xbeb5bf00,0x3eb50000,0x3eb50000,0x3eb53f00,0x3eb50000,0x3eb53f00,
0x3effbf00,0xbd490000,0x3ea2beb5,0xbec63eb5,0x3ef5befb,0xbe153dc8,0x3e71be8e,0xbee23ed5,0x3ee2beed,0xbe713e44,0x3e15be44,0xbef53eed,0x3ec6bed5,0xbea23e8e,0x3d49bdc8,0xbeff3efb,
0xbefb3f00,0x3dc80000,0x3dc80000,0x3efbbf00,0xbed53eed,0x3e8ebe44,0x3e8ebe44,0x3ed5beed,0xbe8e3eb5,0x3ed5beb5,0x3ed5beb5,0x3e8ebeb5,0xbdc83e44,0x3efbbeed,0x3efbbeed,0x3dc8be44,
0x3ef5bf00,0xbe150000,0xbee23eb5,0xbe713eb5,0x3ea2bed5,0xbec63e8e,0xbeff3efb,0x3d493dc8,0x3d49be44,0xbeff3eed,0xbec63eed,0x3ea2be44,0xbe713dc8,0xbee23efb,0xbe153e8e,0x3ef5bed5,
0xbeed3f00,0x3e440000,0x3eedbf00,0xbe440000,0xbe443eb5,0x3eedbeb5,0x3e44beb5,0xbeed3eb5,0x3e440000,0x3eedbf00,0xbe440000,0xbeed3f00,0x3eedbeb5,0x3e44beb5,0xbeed3eb5,0xbe443eb5,
0x3ee2bf00,0xbe710000,0xbe153eb5,0x3ef5beb5,0x3d49be8e,0xbeff3ed5,0x3ea2bdc8,0x3ec6befb,0xbec63e44,0xbea23eed,0x3effbeed,0xbd49be44,0xbef53efb,0x3e153dc8,0x3e71bed5,0xbee23e8e,
0xbed53f00,0x3e8e0000,0xbe8e0000,0xbed53f00,0x3dc83e44,0x3efbbeed,0xbefb3eed,0x3dc83e44,0x3efbbeb5,0x3dc8beb5,0xbdc83eb5,0x3efbbeb5,0x3e8ebeed,0xbed53e44,0x3ed5be44,0x3e8ebeed,
0x3ec6bf00,0xbea20000,0x3effbeb5,0x3d49beb5,0xbe71bdc8,0xbee23efb,0x3e15bed5,0xbef53e8e,0xbef53eed,0x3e153e44,0xbee23e44,0xbe713eed,0x3d493e8e,0x3effbed5,0xbea23efb,0x3ec6bdc8,
0xbeb53f00,0xbeb50000,0xbeb53f00,0xbeb50000,0x3eb50000,0xbeb53f00,0x3eb50000,0xbeb53f00,0x3eb5bf00,0x3eb50000,0x3eb5bf00,0x3eb50000,0xbeb50000,0x3eb5bf00,0xbeb50000,0x3eb5bf00,
0xbd49bf00,0xbeff0000,0xbec6beb5,0xbea23eb5,0x3e153efb,0x3ef5bdc8,0x3ee23e8e,0x3e71bed5,0xbe71beed,0xbee23e44,0xbef5be44,0xbe153eed,0x3ea23ed5,0x3ec6be8e,0x3eff3dc8,0x3d49befb,
0x3dc83f00,0x3efb0000,0x3efb0000,0xbdc8bf00,0xbe8ebeed,0xbed53e44,0xbed53e44,0x3e8e3eed,0x3ed53eb5,0x3e8ebeb5,0x3e8ebeb5,0xbed5beb5,0xbefbbe44,0xbdc83eed,0xbdc83eed,0x3efb3e44,
0xbe15bf00,0xbef50000,0xbe713eb5,0x3ee23eb5,0x3ec63ed5,0x3ea2be8e,0xbd49befb,0xbeffbdc8,0xbeffbe44,0xbd493eed,0x3ea23eed,0x3ec6be44,0x3ee2bdc8,0xbe71befb,0xbef5be8e,0xbe153ed5,
0x3e443f00,0x3eed0000,0xbe44bf00,0xbeed0000,0xbeedbeb5,0xbe443eb5,0x3eed3eb5,0x3e44beb5,0x3eed0000,0xbe44bf00,0xbeed0000,0x3e443f00,0xbe443eb5,0x3eed3eb5,0x3e44beb5,0xbeedbeb5,
0xbe71bf00,0xbee20000,0x3ef53eb5,0x3e15beb5,0x3eff3e8e,0x3d49bed5,0xbec63dc8,0x3ea23efb,0xbea23e44,0x3ec63eed,0xbd49beed,0xbeffbe44,0xbe15befb,0xbef5bdc8,0x3ee23ed5,0x3e71be8e,
0x3e8e3f00,0x3ed50000,0xbed50000,0x3e8e3f00,0xbefbbe44,0x3dc83eed,0xbdc8beed,0xbefbbe44,0x3dc8beb5,0xbefbbeb5,0x3efb3eb5,0x3dc8beb5,0x3ed53eed,0x3e8ebe44,0xbe8e3e44,0x3ed53eed,
0xbea2bf00,0xbec60000,0x3d49beb5,0xbeffbeb5,0x3ee23dc8,0xbe71befb,0x3ef53ed5,0x3e15be8e,0x3e153eed,0x3ef53e44,0xbe713e44,0x3ee23eed,0xbeffbe8e,0x3d493ed5,0xbec6befb,0xbea23dc8,
0x3f003f00,0xbf003f00,0x3f003f00,0xbf003f00,0x3f003f00,0xbf003f00,0x3f003f00,0xbf003f00,0x3f003f00,0xbf003f00,0x3f003f00,0xbf003f00,0x3f003f00,0xbf003f00,0x3f003f00,0xbf003f00,
0x3d490000,0x3eff3f00,0x3ec63eb5,0x3ea23eb5,0x3e153dc8,0x3ef53efb,0x3ee23ed5,0x3e713e8e,0x3e713e44,0x3ee23eed,0x3ef53eed,0x3e153e44,0x3ea23e8e,0x3ec63ed5,0x3eff3efb,0x3d493dc8,
0xbefbbf00,0x3dc80000,0x3dc80000,0x3efb3f00,0xbed5beed,0x3e8e3e44,0x3e8e3e44,0x3ed53eed,0xbe8ebeb5,0x3ed53eb5,0x3ed53eb5,0x3e8e3eb5,0xbdc8be44,0x3efb3eed,0x3efb3eed,0x3dc83e44,
0xbe150000,0xbef5bf00,0xbe71beb5,0x3ee23eb5,0xbec6be8e,0xbea2bed5,0x3d49bdc8,0x3eff3efb,0xbeffbeed,0xbd49be44,0x3ea23e44,0x3ec63eed,0xbee2befb,0x3e713dc8,0x3ef53ed5,0x3e153e8e,
0x3eed3f00,0xbe440000,0xbeedbf00,0x3e440000,0x3e443eb5,0xbeedbeb5,0xbe44beb5,0x3eed3eb5,0xbe440000,0xbeedbf00,0x3e440000,0x3eed3f00,0xbeedbeb5,0xbe44beb5,0x3eed3eb5,0x3e443eb5,
0x3e710000,0x3ee23f00,0xbef5beb5,0xbe15beb5,0x3eff3ed5,0x3d493e8e,0xbec6befb,0x3ea23dc8,0x3ea23eed,0xbec6be44,0x3d49be44,0x3eff3eed,0xbe153dc8,0xbef5befb,0x3ee23e8e,0x3e713ed5,
0xbed5bf00,0x3e8e0000,0xbe8e0000,0xbed5bf00,0x3dc8be44,0x3efb3eed,0xbefbbeed,0x3dc8be44,0x3efb3eb5,0x3dc83eb5,0xbdc8beb5,0x3efb3eb5,0x3e8e3eed,0xbed5be44,0x3ed53e44,0x3e8e3eed,
0xbea20000,0xbec6bf00,0x3d493eb5,0xbeffbeb5,0xbee2befb,0x3e71bdc8,0xbef5be8e,0xbe15bed5,0x3e15be44,0x3ef53eed,0xbe71beed,0x3ee23e44,0x3eff3ed5,0xbd493e8e,0x3ec63dc8,0x3ea23efb,
0x3f00,0xbf000000,0x3f00,0xbf000000,0xbf00,0x3f000000,0xbf00,0x3f000000,0x3f00,0xbf000000,0x3f00,0xbf000000,0xbf00,0x3f000000,0xbf00,0x3f000000,
0x3eff0000,0xbd493f00,0x3ea23eb5,0xbec63eb5,0xbef5bdc8,0x3e15befb,0xbe71bed5,0x3ee2be8e,0x3ee23e44,0xbe713eed,0x3e153eed,0xbef53e44,0xbec6be8e,0x3ea2bed5,0xbd49befb,0x3effbdc8,
0x3dc8bf00,0x3efb0000,0x3efb0000,0xbdc83f00,0xbe8e3eed,0xbed5be44,0xbed5be44,0x3e8ebeed,0x3ed5beb5,0x3e8e3eb5,0x3e8e3eb5,0xbed53eb5,0xbefb3e44,0xbdc8beed,0xbdc8beed,0x3efbbe44,
0xbef50000,0x3e15bf00,0x3ee2beb5,0x3e713eb5,0x3ea23e8e,0xbec63ed5,0xbeff3dc8,0x3d49befb,0xbd49beed,0x3effbe44,0x3ec63e44,0xbea23eed,0xbe713efb,0xbee2bdc8,0xbe15bed5,0x3ef5be8e,
0xbe443f00,0xbeed0000,0x3e44bf00,0x3eed0000,0x3eedbeb5,0x3e443eb5,0xbeed3eb5,0xbe44beb5,0xbeed0000,0x3e44bf00,0x3eed0000,0xbe443f00,0x3e443eb5,0xbeed3eb5,0xbe44beb5,0x3eedbeb5,
0x3ee20000,0xbe713f00,0xbe15beb5,0x3ef5beb5,0xbd49bed5,0x3effbe8e,0xbea23efb,0xbec6bdc8,0xbec63eed,0xbea2be44,0x3effbe44,0xbd493eed,0x3ef5bdc8,0xbe153efb,0xbe71be8e,0x3ee2bed5,
0x3e8ebf00,0x3ed50000,0xbed50000,0x3e8ebf00,0xbefb3e44,0x3dc8beed,0xbdc83eed,0xbefb3e44,0x3dc83eb5,0xbefb3eb5,0x3efbbeb5,0x3dc83eb5,0x3ed5beed,0x3e8e3e44,0xbe8ebe44,0x3ed5beed,
0xbec60000,0x3ea2bf00,0xbeff3eb5,0xbd49beb5,0xbe713efb,0xbee23dc8,0x3e153e8e,0xbef53ed5,0x3ef5be44,0xbe153eed,0x3ee2beed,0x3e713e44,0x3d49bed5,0x3effbe8e,0xbea2bdc8,0x3ec6befb,
0x3eb53f00,0xbeb50000,0x3eb53f00,0xbeb50000,0xbeb50000,0xbeb5bf00,0xbeb50000,0xbeb5bf00,0xbeb5bf00,0x3eb50000,0xbeb5bf00,0x3eb50000,0x3eb50000,0x3eb53f00,0x3eb50000,0x3eb53f00,
0xbd490000,0xbeff3f00,0xbec63eb5,0xbea23eb5,0xbe153dc8,0xbef53efb,0xbee23ed5,0xbe713e8e,0xbe713e44,0xbee23eed,0xbef53eed,0xbe153e44,0xbea23e8e,0xbec63ed5,0xbeff3efb,0xbd493dc8,
0x3efbbf00,0xbdc80000,0xbdc80000,0xbefb3f00,0x3ed5beed,0xbe8e3e44,0xbe8e3e44,0xbed53eed,0x3e8ebeb5,0xbed53eb5,0xbed53eb5,0xbe8e3eb5,0x3dc8be44,0xbefb3eed,0xbefb3eed,0xbdc83e44,
0x3e150000,0x3ef5bf00,0x3e71beb5,0xbee23eb5,0x3ec6be8e,0x3ea2bed5,0xbd49bdc8,0xbeff3efb,0x3effbeed,0x3d49be44,0xbea23e44,0xbec63eed,0x3ee2befb,0xbe713dc8,0xbef53ed5,0xbe153e8e,
0xbeed3f00,0x3e440000,0x3eedbf00,0xbe440000,0xbe443eb5,0x3eedbeb5,0x3e44beb5,0xbeed3eb5,0x3e440000,0x3eedbf00,0xbe440000,0xbeed3f00,0x3eedbeb5,0x3e44beb5,0xbeed3eb5,0xbe443eb5,
0xbe710000,0xbee23f00,0x3ef5beb5,0x3e15beb5,0xbeff3ed5,0xbd493e8e,0x3ec6befb,0xbea23dc8,0xbea23eed,0x3ec6be44,0xbd49be44,0xbeff3eed,0x3e153dc8,0x3ef5befb,0xbee23e8e,0xbe713ed5,
0x3ed5bf00,0xbe8e0000,0x3e8e0000,0x3ed5bf00,0xbdc8be44,0xbefb3eed,0x3efbbeed,0xbdc8be44,0xbefb3eb5,0xbdc83eb5,0x3dc8beb5,0xbefb3eb5,0xbe8e3eed,0x3ed5be44,0xbed53e44,0xbe8e3eed,
0x3ea20000,0x3ec6bf00,0xbd493eb5,0x3effbeb5,0x3ee2befb,0xbe71bdc8,0x3ef5be8e,0x3e15bed5,0xbe15be44,0xbef53eed,0x3e71beed,0xbee23e44,0xbeff3ed5,0x3d493e8e,0xbec63dc8,0xbea23efb,
0xbeb53f00,0xbeb50000,0xbeb53f00,0xbeb50000,0x3eb50000,0xbeb53f00,0x3eb50000,0xbeb53f00,0x3eb5bf00,0x3eb50000,0x3eb5bf00,0x3eb50000,0xbeb50000,0x3eb5bf00,0xbeb50000,0x3eb5bf00,
0xbeff0000,0x3d493f00,0xbea23eb5,0x3ec63eb5,0x3ef5bdc8,0xbe15befb,0x3e71bed5,0xbee2be8e,0xbee23e44,0x3e713eed,0xbe153eed,0x3ef53e44,0x3ec6be8e,0xbea2bed5,0x3d49befb,0xbeffbdc8,
0xbdc8bf00,0xbefb0000,0xbefb0000,0x3dc83f00,0x3e8e3eed,0x3ed5be44,0x3ed5be44,0xbe8ebeed,0xbed5beb5,0xbe8e3eb5,0xbe8e3eb5,0x3ed53eb5,0x3efb3e44,0x3dc8beed,0x3dc8beed,0xbefbbe44,
0x3ef50000,0xbe15bf00,0xbee2beb5,0xbe713eb5,0xbea23e8e,0x3ec63ed5,0x3eff3dc8,0xbd49befb,0x3d49beed,0xbeffbe44,0xbec63e44,0x3ea23eed,0x3e713efb,0x3ee2bdc8,0x3e15bed5,0xbef5be8e,
0x3e443f00,0x3eed0000,0xbe44bf00,0xbeed0000,0xbeedbeb5,0xbe443eb5,0x3eed3eb5,0x3e44beb5,0x3eed0000,0xbe44bf00,0xbeed0000,0x3e443f00,0xbe443eb5,0x3eed3eb5,0x3e44beb5,0xbeedbeb5,
0xbee20000,0x3e713f00,0x3e15beb5,0xbef5beb5,0x3d49bed5,0xbeffbe8e,0x3ea23efb,0x3ec6bdc8,0x3ec63eed,0x3ea2be44,0xbeffbe44,0x3d493eed,0xbef5bdc8,0x3e153efb,0x3e71be8e,0xbee2bed5,
0xbe8ebf00,0xbed50000,0x3ed50000,0xbe8ebf00,0x3efb3e44,0xbdc8beed,0x3dc83eed,0x3efb3e44,0xbdc83eb5,0x3efb3eb5,0xbefbbeb5,0xbdc83eb5,0xbed5beed,0xbe8e3e44,0x3e8ebe44,0xbed5beed,
0x3ec60000,0xbea2bf00,0x3eff3eb5,0x3d49beb5,0x3e713efb,0x3ee23dc8,0xbe153e8e,0x3ef53ed5,0xbef5be44,0x3e153eed,0xbee2beed,0xbe713e44,0xbd49bed5,0xbeffbe8e,0x3ea2bdc8,0xbec6befb,
0x3f800000,0x0,0x3f800000,0x0,0x3f800000,0x0,0x3f800000,0x0,0x3f800000,0x0,0x3f800000,0x0,0x3f800000,0x0,0x3f800000,0x0,
0x3f800000,0x0,0x3f7fec43,0xbcc90ab0,0x3f7fb10f,0xbd48fb30,0x3f7f4e6d,0xbd96a905,0x3f7ec46d,0xbdc8bd36,0x3f7e1324,0xbdfab273,0x3f7d3aac,0xbe164083,0x3f7c3b28,0xbe2f10a2,
0x3f800000,0x0,0x3f7ffec4,0xbbc90f88,0x3f7ffb11,0xbc490e90,0x3f7ff4e6,0xbc96c9b6,0x3f7fec43,0xbcc90ab0,0x3f7fe129,0xbcfb49ba,0x3f7fd397,0xbd16c32c,0x3f7fc38f,0xbd2fe007,
0x3f800000,0x0,0x3f7fe129,0xbcfb49ba,0x3f7f84ab,0xbd7b2b74,0x3f7eea9d,0xbdbc3ac3,0x3f7e1324,0xbdfab273,0x3f7cfe73,0xbe1c76de,0x3f7baccd,0xbe3b6ecf,0x3f7a1e84,0xbe5a3997,
0x3f800000,0x0,0x3f7ffb11,0xbc490e90,0x3f7fec43,0xbcc90ab0,0x3f7fd397,0xbd16c32c,0x3f7fb10f,0xbd48fb30,0x3f7f84ab,0xbd7b2b74,0x3f7f4e6d,0xbd96a905,0x3f7f0e58,0xbdafb680,
0x3f800000,0x0,0x3f7fd397,0xbd16c32c,0x3f7f4e6d,0xbd96a905,0x3f7e70b0,0xbde1bc2e,0x3f7d3aac,0xbe164083,0x3f7baccd,0xbe3b6ecf,0x3f79c79d,0xbe605c13,0x3f778bc5,0xbe827dc0,
0x3f800000,0x0,0x3f7ff4e6,0xbc96c9b6,0x3f7fd397,0xbd16c32c,0x3f7f9c18,0xbd621469,0x3f7f4e6d,0xbd96a905,0x3f7eea9d,0xbdbc3ac3,0x3f7e70b0,0xbde1bc2e,0x3f7de0b1,0xbe039502,
0x3f800000,0x0,0x3f7fc38f,0xbd2fe007,0x3f7f0e58,0xbdafb680,0x3f7de0b1,0xbe039502,0x3f7c3b28,0xbe2f10a2,0x3f7a1e84,0xbe5a3997,0x3f778bc5,0xbe827dc0,0x3f748422,0xbe97a117,
0x3f800000,0x0,0x3f7fb10f,0xbd48fb30,0x3f7ec46d,0xbdc8bd36,0x3f7d3aac,0xbe164083,0x3f7b14be,0xbe47c5c2,0x3f7853f8,0xbe78cfcc,0x3f74fa0b,0xbe94a031,0x3f710908,0xbeac7cd4,
0x3f800000,0x0,0x3f7f4e6d,0xbd96a905,0x3f7d3aac,0xbe164083,0x3f79c79d,0xbe605c13,0x3f74fa0b,0xbe94a031,0x3f6ed89e,0xbeb8442a,0x3f676bd8,0xbedae880,0x3f5ebe05,0xbefc5d27,
0x3f800000,0x0,0x3f7f9c18,0xbd621469,0x3f7e70b0,0xbde1bc2e,0x3f7c7eb0,0xbe28defc,0x3f79c79d,0xbe605c13,0x3f764d97,0xbe8b9507,0x3f721352,0xbea68f12,0x3f6d1c1d,0xbec1071e,
0x3f800000,0x0,0x3f7f2f9d,0xbda3308c,0x3f7cbfc9,0xbe22abb6,0x3f78b47b,0xbe72b651,0x3f731447,0xbea09ae5,0x3f6be858,0xbec6d529,0x3f633c5a,0xbeebcbbb,0x3f591e6a,0xbf07a136,
0x3f800000,0x0,0x3f7f84ab,0xbd7b2b74,0x3f7e1324,0xbdfab273,0x3f7baccd,0xbe3b6ecf,0x3f7853f8,0xbe78cfcc,0x3f740bdd,0xbe9aa086,0x3f6ed89e,0xbeb8442a,0x3f68bf3c,0xbed53641,
0x3f800000,0x0,0x3f7f0e58,0xbdafb680,0x3f7c3b28,0xbe2f10a2,0x3f778bc5,0xbe827dc0,0x3f710908,0xbeac7cd4,0x3f68bf3c,0xbed53641,0x3f5ebe05,0xbefc5d27,0x3f531849,0xbf10d3cd,
0x3f800000,0x0,0x3f7f6ac7,0xbd8a200a,0x3f7dabcc,0xbe09cf86,0x3f7ac516,0xbe4dee60,0x3f76ba07,0xbe888e93,0x3f718f57,0xbea986c4,0x3f6b4b0c,0xbec9b953,0x3f63f473,0xbee900b7,
0x3f800000,0x0,0x3f7eea9d,0xbdbc3ac3,0x3f7baccd,0xbe3b6ecf,0x3f764d97,0xbe8b9507,0x3f6ed89e,0xbeb8442a,0x3f655e0b,0xbee363fa,0x3f59f26a,0xbf064b82,0x3f4cae79,0xbf19c200,
0x3f800000,0x0,0x3f7ec46d,0xbdc8bd36,0x3f7b14be,0xbe47c5c2,0x3f74fa0b,0xbe94a031,0x3f6c835e,0xbec3ef15,0x3f61c598,0xbef15aea,0x3f54db31,0xbf0e39da,0x3f45e403,0xbf226799,
0x3f800000,0x0,0x3f7e1324,0xbdfab273,0x3f7853f8,0xbe78cfcc,0x3f6ed89e,0xbeb8442a,0x3f61c598,0xbef15aea,0x3f514d3d,0xbf13682a,0x3f3daef9,0xbf2beb4a,0x3f273656,0xbf41d870,
0x3f800000,0x0,0x3f7e9bc9,0xbdd53db9,0x3f7a7302,0xbe541501,0x3f73913f,0xbe9d9e78,0x3f6a09a7,0xbecf7bca,0x3f5df6be,0xbeff17b2,0x3f4f7a1f,0xbf15f6d9,0x3f3ebc1b,0xbf2ac082,
0x3f800000,0x0,0x3f7de0b1,0xbe039502,0x3f778bc5,0xbe827dc0,0x3f6d1c1d,0xbec1071e,0x3f5ebe05,0xbefc5d27,0x3f4cae79,0xbf19c200,0x3f373a23,0xbf32c8c9,0x3f1ebc12,0xbf48d8b3,
0x3f800000,0x0,0x3f7e70b0,0xbde1bc2e,0x3f79c79d,0xbe605c13,0x3f721352,0xbea68f12,0x3f676bd8,0xbedae880,0x3f59f26a,0xbf064b82,0x3f49d112,0xbf1d7fd1,0x3f373a23,0xbf32c8c9,
0x3f800000,0x0,0x3f7dabcc,0xbe09cf86,0x3f76ba07,0xbe888e93,0x3f6b4b0c,0xbec9b953,0x3f5b941a,0xbf039c3d,0x3f47de65,0xbf1ff6cb,0x3f3085bb,0xbf396842,0x3f15f6d9,0xbf4f7a1f,
0x3f800000,0x0,0x3f7e4323,0xbdee3876,0x3f791298,0xbe6c9a7f,0x3f708066,0xbeaf713a,0x3f64aa59,0xbee63375,0x3f55b993,0xbf0cead0,0x3f43e200,0xbf24d225,0x3f2f61a5,0xbf3a7ca4,
0x3f800000,0x0,0x3f7d7474,0xbe1008b7,0x3f75dec6,0xbe8e9a22,0x3f696591,0xbed25a09,0x3f584853,0xbf08f59b,0x3f42de29,0xbf26050a,0x3f299415,0xbf3fc767,0x3f0cead0,0xbf55b993,
0x3f800000,0x0,0x3f7d3aac,0xbe164083,0x3f74fa0b,0xbe94a031,0x3f676bd8,0xbedae880,0x3f54db31,0xbf0e39da,0x3f3daef9,0xbf2beb4a,0x3f226799,0xbf45e403,0x3f039c3d,0xbf5b941a,
0x3f800000,0x0,0x3f7c3b28,0xbe2f10a2,0x3f710908,0xbeac7cd4,0x3f5ebe05,0xbefc5d27,0x3f45e403,0xbf226799,0x3f273656,0xbf41d870,0x3f039c3d,0xbf5b941a,0x3eb8442a,0xbf6ed89e,
0x3f800000,0x0,0x3f7cfe73,0xbe1c76de,0x3f740bdd,0xbe9aa086,0x3f655e0b,0xbee363fa,0x3f514d3d,0xbf13682a,0x3f385216,0xbf31a81d,0x3f1b02c6,0xbf4bbbf8,0x3ef41f07,0xbf6106f2,
0x3f800000,0x0,0x3f7bf531,0xbe354098,0x3f6ff573,0xbeb263ef,0x3f5c61c7,0xbf0242b1,0x3f41d870,0xbf273656,0x3f212ff9,0xbf46e22a,0x3ef6e0cb,0xbf604621,0x3ea395c5,0xbf7294f8,
0x3f800000,0x0,0x3f7cbfc9,0xbe22abb6,0x3f731447,0xbea09ae5,0x3f633c5a,0xbeebcbbb,0x3f4d9f02,0xbf187fc0,0x3f32c8c9,0xbf373a23,0x3f13682a,0xbf514d3d,0x3ee0924f,0xbf660f88,
0x3f800000,0x0,0x3f7baccd,0xbe3b6ecf,0x3f6ed89e,0xbeb8442a,0x3f59f26a,0xbf064b82,0x3f3daef9,0xbf2beb4a,0x3f1b02c6,0xbf4bbbf8,0x3ee63375,0xbf64aa59,0x3e8e9a22,0xbf75dec6,
0x3f800000,0x0,0x3f7c7eb0,0xbe28defc,0x3f721352,0xbea68f12,0x3f6106f2,0xbef41f07,0x3f49d112,0xbf1d7fd1,0x3f2d1469,0xbf3ca003,0x3f0b9a6b,0xbf5695e5,0x3ecc9b8b,0xbf6aab7b,
0x3f800000,0x0,0x3f7b61fc,0xbe419b37,0x3f6db293,0xbebe1d4a,0x3f577026,0xbf0a48ad,0x3f396842,0xbf3085bb,0x3f14b039,0xbf5064af,0x3ed53641,0xbf68bf3c,0x3e72b651,0xbf78b47b,
0x3f800000,0x0,0x3f800000,0x0,0x3f800000,0x0,0x3f800000,0x0,0x3f800000,0x0,0x3f800000,0x0,0x3f800000,0x0,0x3f800000,0x0,
0x3f7b14be,0xbe47c5c2,0x3f79c79d,0xbe605c13,0x3f7853f8,0xbe78cfcc,0x3f76ba07,0xbe888e93,0x3f74fa0b,0xbe94a031,0x3f731447,0xbea09ae5,0x3f710908,0xbeac7cd4,0x3f6ed89e,0xbeb8442a,
0x3f7fb10f,0xbd48fb30,0x3f7f9c18,0xbd621469,0x3f7f84ab,0xbd7b2b74,0x3f7f6ac7,0xbd8a200a,0x3f7f4e6d,0xbd96a905,0x3f7f2f9d,0xbda3308c,0x3f7f0e58,0xbdafb680,0x3f7eea9d,0xbdbc3ac3,
0x3f7853f8,0xbe78cfcc,0x3f764d97,0xbe8b9507,0x3f740bdd,0xbe9aa086,0x3f718f57,0xbea986c4,0x3f6ed89e,0xbeb8442a,0x3f6be858,0xbec6d529,0x3f68bf3c,0xbed53641,0x3f655e0b,0xbee363fa,
0x3f7ec46d,0xbdc8bd36,0x3f7e70b0,0xbde1bc2e,0x3f7e1324,0xbdfab273,0x3f7dabcc,0xbe09cf86,0x3f7d3aac,0xbe164083,0x3f7cbfc9,0xbe22abb6,0x3f7c3b28,0xbe2f10a2,0x3f7baccd,0xbe3b6ecf,
0x3f74fa0b,0xbe94a031,0x3f721352,0xbea68f12,0x3f6ed89e,0xbeb8442a,0x3f6b4b0c,0xbec9b953,0x3f676bd8,0xbedae880,0x3f633c5a,0xbeebcbbb,0x3f5ebe05,0xbefc5d27,0x3f59f26a,0xbf064b82,
0x3f7d3aac,0xbe164083,0x3f7c7eb0,0xbe28defc,0x3f7baccd,0xbe3b6ecf,0x3f7ac516,0xbe4dee60,0x3f79c79d,0xbe605c13,0x3f78b47b,0xbe72b651,0x3f778bc5,0xbe827dc0,0x3f764d97,0xbe8b9507,
0x3f710908,0xbeac7cd4,0x3f6d1c1d,0xbec1071e,0x3f68bf3c,0xbed53641,0x3f63f473,0xbee900b7,0x3f5ebe05,0xbefc5d27,0x3f591e6a,0xbf07a136,0x3f531849,0xbf10d3cd,0x3f4cae79,0xbf19c200,
0x3f6c835e,0xbec3ef15,0x3f676bd8,0xbedae880,0x3f61c598,0xbef15aea,0x3f5b941a,0xbf039c3d,0x3f54db31,0xbf0e39da,0x3f4d9f02,0xbf187fc0,0x3f45e403,0xbf226799,0x3f3daef9,0xbf2beb4a,
0x3f54db31,0xbf0e39da,0x3f49d112,0xbf1d7fd1,0x3f3daef9,0xbf2beb4a,0x3f3085bb,0xbf396842,0x3f226799,0xbf45e403,0x3f13682a,0xbf514d3d,0x3f039c3d,0xbf5b941a,0x3ee63375,0xbf64aa59,
0x3f676bd8,0xbedae880,0x3f6106f2,0xbef41f07,0x3f59f26a,0xbf064b82,0x3f5233c6,0xbf121eb0,0x3f49d112,0xbf1d7fd1,0x3f40d0da,0xbf286605,0x3f373a23,0xbf32c8c9,0x3f2d1469,0xbf3ca003,
0x3f4d9f02,0xbf187fc0,0x3f40d0da,0xbf286605,0x3f32c8c9,0xbf373a23,0x3f239da9,0xbf44e3f5,0x3f13682a,0xbf514d3d,0x3f0242b1,0xbf5c61c7,0x3ee0924f,0xbf660f88,0x3ebb31a0,0xbf6e46be,
0x3f61c598,0xbef15aea,0x3f59f26a,0xbf064b82,0x3f514d3d,0xbf13682a,0x3f47de65,0xbf1ff6cb,0x3f3daef9,0xbf2beb4a,0x3f32c8c9,0xbf373a23,0x3f273656,0xbf41d870,0x3f1b02c6,0xbf4bbbf8,
0x3f45e403,0xbf226799,0x3f373a23,0xbf32c8c9,0x3f273656,0xbf41d870,0x3f15f6d9,0xbf4f7a1f,0x3f039c3d,0xbf5b941a,0x3ee0924f,0xbf660f88,0x3eb8442a,0xbf6ed89e,0x3e8e9a22,0xbf75dec6,
0x3f5b941a,0xbf039c3d,0x3f5233c6,0xbf121eb0,0x3f47de65,0xbf1ff6cb,0x3f3ca003,0xbf2d1469,0x3f3085bb,0xbf396842,0x3f239da9,0xbf44e3f5,0x3f15f6d9,0xbf4f7a1f,0x3f07a136,0xbf591e6a,
0x3f3daef9,0xbf2beb4a,0x3f2d1469,0xbf3ca003,0x3f1b02c6,0xbf4bbbf8,0x3f07a136,0xbf591e6a,0x3ee63375,0xbf64aa59,0x3ebb31a0,0xbf6e46be,0x3e8e9a22,0xbf75dec6,0x3e419b37,0xbf7b61fc,
0x3f3504f3,0xbf3504f3,0x3f226799,0xbf45e403,0x3f0e39da,0xbf54db31,0x3ef15aea,0xbf61c598,0x3ec3ef15,0xbf6c835e,0x3e94a031,0xbf74fa0b,0x3e47c5c2,0xbf7b14be,0x3dc8bd36,0xbf7ec46d,
0x3f0e39da,0xbf54db31,0x3ee63375,0xbf64aa59,0x3eac7cd4,0xbf710908,0x3e605c13,0xbf79c79d,0x3dc8bd36,0xbf7ec46d,0xbcc90ab0,0xbf7fec43,0xbe164083,0xbf7d3aac,0xbe888e93,0xbf76ba07,
0x3f2beb4a,0xbf3daef9,0x3f173c07,0xbf4e8d90,0x3f00e7e4,0xbf5d2d53,0x3ed25a09,0xbf696591,0x3ea09ae5,0xbf731447,0x3e5a3997,0xbf7a1e84,0x3de1bc2e,0xbf7e70b0,0x3bc90f88,0xbf7ffec4,
0x3f039c3d,0xbf5b941a,0x3ecc9b8b,0xbf6aab7b,0x3e8e9a22,0xbf75dec6,0x3e1c76de,0xbf7cfe73,0x3cc90ab0,0xbf7fec43,0xbdd53db9,0xbf7e9bc9,0xbe6c9a7f,0xbf791298,0xbeb554ec,0xbf6f6830,
0x3f226799,0xbf45e403,0x3f0b9a6b,0xbf5695e5,0x3ee63375,0xbf64aa59,0x3eb263ef,0xbf6ff573,0x3e78cfcc,0xbf7853f8,0x3e09cf86,0xbf7dabcc,0x3cc90ab0,0xbf7fec43,0xbdafb680,0xbf7f0e58,
0x3ef15aea,0xbf61c598,0x3eb263ef,0xbf6ff573,0x3e605c13,0xbf79c79d,0x3dafb680,0xbf7f0e58,0xbd48fb30,0xbf7fb10f,0xbe3b6ecf,0xbf7baccd,0xbea09ae5,0xbf731447,0xbee0924f,0xbf660f88,
0x3f187fc0,0xbf4d9f02,0x3eff17b2,0xbf5df6be,0x3ec9b953,0xbf6b4b0c,0x3e919ddd,0xbf756d97,0x3e2f10a2,0xbf7c3b28,0x3d621469,0xbf7f9c18,0xbd7b2b74,0xbf7f84ab,0xbe354098,0xbf7bf531,
0x3edae880,0xbf676bd8,0x3e97a117,0xbf748422,0x3e22abb6,0xbf7cbfc9,0x3c96c9b6,0xbf7ff4e6,0xbdfab273,0xbf7e1324,0xbe8586ce,0xbf772417,0xbec9b953,0xbf6b4b0c,0xbf04f484,0xbf5ac450,
0x3ec3ef15,0xbf6c835e,0x3e78cfcc,0xbf7853f8,0x3dc8bd36,0xbf7ec46d,0xbd48fb30,0xbf7fb10f,0xbe47c5c2,0xbf7b14be,0xbeac7cd4,0xbf710908,0xbef15aea,0xbf61c598,0xbf187fc0,0xbf4d9f02,
0x3e47c5c2,0xbf7b14be,0x3cc90ab0,0xbf7fec43,0xbe164083,0xbf7d3aac,0xbea09ae5,0xbf731447,0xbef15aea,0xbf61c598,0xbf1d7fd1,0xbf49d112,0xbf3daef9,0xbf2beb4a,0xbf584853,0xbf08f59b,
0x3eac7cd4,0xbf710908,0x3e419b37,0xbf7b61fc,0x3d16c32c,0xbf7fd397,0xbdee3876,0xbf7e4323,0xbe888e93,0xbf76ba07,0xbed25a09,0xbf696591,0xbf0b9a6b,0xbf5695e5,0xbf2ac082,0xbf3ebc1b,
0x3e164083,0xbf7d3aac,0xbcfb49ba,0xbf7fe129,0xbe541501,0xbf7a7302,0xbec1071e,0xbf6d1c1d,0xbf08f59b,0xbf584853,0xbf2d1469,0xbf3ca003,0xbf4bbbf8,0xbf1b02c6,0xbf63f473,0xbee900b7,
0x3e94a031,0xbf74fa0b,0x3e09cf86,0xbf7dabcc,0xbcc90ab0,0xbf7fec43,0xbe3b6ecf,0xbf7baccd,0xbeac7cd4,0xbf710908,0xbef6e0cb,0xbf604621,0xbf1d7fd1,0xbf49d112,0xbf3b8f3b,0xbf2e3bde,
0x3dc8bd36,0xbf7ec46d,0xbdafb680,0xbf7f0e58,0xbe888e93,0xbf76ba07,0xbee0924f,0xbf660f88,0xbf187fc0,0xbf4d9f02,0xbf3b8f3b,0xbf2e3bde,0xbf584853,0xbf08f59b,0xbf6db293,0xbebe1d4a,
0x3e78cfcc,0xbf7853f8,0x3da3308c,0xbf7f2f9d,0xbdafb680,0xbf7f0e58,0xbe7ee6e1,0xbf77f110,0xbecf7bca,0xbf6a09a7,0xbf0cead0,0xbf55b993,0xbf2e3bde,0xbf3b8f3b,0xbf4ac77f,0xbf1c420c,
0x3d48fb30,0xbf7fb10f,0xbe1008b7,0xbf7d7474,0xbea68f12,0xbf721352,0xbeff17b2,0xbf5df6be,0xbf273656,0xbf41d870,0xbf48d8b3,0xbf1ebc12,0xbf633c5a,0xbeebcbbb,0xbf756d97,0xbe919ddd,
0x3f800000,0x0,0x3f800000,0x0,0x3f800000,0x0,0x3f800000,0x0,0x3f800000,0x0,0x3f800000,0x0,0x3f800000,0x0,0x3f800000,0x0,
0x3f6c835e,0xbec3ef15,0x3f6a09a7,0xbecf7bca,0x3f676bd8,0xbedae880,0x3f64aa59,0xbee63375,0x3f61c598,0xbef15aea,0x3f5ebe05,0xbefc5d27,0x3f5b941a,0xbf039c3d,0x3f584853,0xbf08f59b,
0x3f7ec46d,0xbdc8bd36,0x3f7e9bc9,0xbdd53db9,0x3f7e70b0,0xbde1bc2e,0x3f7e4323,0xbdee3876,0x3f7e1324,0xbdfab273,0x3f7de0b1,0xbe039502,0x3f7dabcc,0xbe09cf86,0x3f7d7474,0xbe1008b7,
0x3f61c598,0xbef15aea,0x3f5df6be,0xbeff17b2,0x3f59f26a,0xbf064b82,0x3f55b993,0xbf0cead0,0x3f514d3d,0xbf13682a,0x3f4cae79,0xbf19c200,0x3f47de65,0xbf1ff6cb,0x3f42de29,0xbf26050a,
0x3f7b14be,0xbe47c5c2,0x3f7a7302,0xbe541501,0x3f79c79d,0xbe605c13,0x3f791298,0xbe6c9a7f,0x3f7853f8,0xbe78cfcc,0x3f778bc5,0xbe827dc0,0x3f76ba07,0xbe888e93,0x3f75dec6,0xbe8e9a22,
0x3f54db31,0xbf0e39da,0x3f4f7a1f,0xbf15f6d9,0x3f49d112,0xbf1d7fd1,0x3f43e200,0xbf24d225,0x3f3daef9,0xbf2beb4a,0x3f373a23,0xbf32c8c9,0x3f3085bb,0xbf396842,0x3f299415,0xbf3fc767,
0x3f74fa0b,0xbe94a031,0x3f73913f,0xbe9d9e78,0x3f721352,0xbea68f12,0x3f708066,0xbeaf713a,0x3f6ed89e,0xbeb8442a,0x3f6d1c1d,0xbec1071e,0x3f6b4b0c,0xbec9b953,0x3f696591,0xbed25a09,
0x3f45e403,0xbf226799,0x3f3ebc1b,0xbf2ac082,0x3f373a23,0xbf32c8c9,0x3f2f61a5,0xbf3a7ca4,0x3f273656,0xbf41d870,0x3f1ebc12,0xbf48d8b3,0x3f15f6d9,0xbf4f7a1f,0x3f0cead0,0xbf55b993,
0x3f3504f3,0xbf3504f3,0x3f2beb4a,0xbf3daef9,0x3f226799,0xbf45e403,0x3f187fc0,0xbf4d9f02,0x3f0e39da,0xbf54db31,0x3f039c3d,0xbf5b941a,0x3ef15aea,0xbf61c598,0x3edae880,0xbf676bd8,
0x3ec3ef15,0xbf6c835e,0x3ea09ae5,0xbf731447,0x3e78cfcc,0xbf7853f8,0x3e2f10a2,0xbf7c3b28,0x3dc8bd36,0xbf7ec46d,0x3cc90ab0,0xbf7fec43,0xbd48fb30,0xbf7fb10f,0xbdfab273,0xbf7e1324,
0x3f226799,0xbf45e403,0x3f173c07,0xbf4e8d90,0x3f0b9a6b,0xbf5695e5,0x3eff17b2,0xbf5df6be,0x3ee63375,0xbf64aa59,0x3ecc9b8b,0xbf6aab7b,0x3eb263ef,0xbf6ff573,0x3e97a117,0xbf748422,
0x3e94a031,0xbf74fa0b,0x3e5a3997,0xbf7a1e84,0x3e09cf86,0xbf7dabcc,0x3d621469,0xbf7f9c18,0xbcc90ab0,0xbf7fec43,0xbdd53db9,0xbf7e9bc9,0xbe3b6ecf,0xbf7baccd,0xbe8586ce,0xbf772417,
0x3f0e39da,0xbf54db31,0x3f00e7e4,0xbf5d2d53,0x3ee63375,0xbf64aa59,0x3ec9b953,0xbf6b4b0c,0x3eac7cd4,0xbf710908,0x3e8e9a22,0xbf75dec6,0x3e605c13,0xbf79c79d,0x3e22abb6,0xbf7cbfc9,
0x3e47c5c2,0xbf7b14be,0x3de1bc2e,0xbf7e70b0,0x3cc90ab0,0xbf7fec43,0xbd7b2b74,0xbf7f84ab,0xbe164083,0xbf7d3aac,0xbe6c9a7f,0xbf791298,0xbea09ae5,0xbf731447,0xbec9b953,0xbf6b4b0c,
0x3ef15aea,0xbf61c598,0x3ed25a09,0xbf696591,0x3eb263ef,0xbf6ff573,0x3e919ddd,0xbf756d97,0x3e605c13,0xbf79c79d,0x3e1c76de,0xbf7cfe73,0x3dafb680,0xbf7f0e58,0x3c96c9b6,0xbf7ff4e6,
0x3dc8bd36,0xbf7ec46d,0x3bc90f88,0xbf7ffec4,0xbdafb680,0xbf7f0e58,0xbe354098,0xbf7bf531,0xbe888e93,0xbf76ba07,0xbeb554ec,0xbf6f6830,0xbee0924f,0xbf660f88,0xbf04f484,0xbf5ac450,
0x0,0xbf800000,0xbdc8bd36,0xbf7ec46d,0xbe47c5c2,0xbf7b14be,0xbe94a031,0xbf74fa0b,0xbec3ef15,0xbf6c835e,0xbef15aea,0xbf61c598,0xbf0e39da,0xbf54db31,0xbf226799,0xbf45e403,
0xbec3ef15,0xbf6c835e,0xbefc5d27,0xbf5ebe05,0xbf187fc0,0xbf4d9f02,0xbf3085bb,0xbf396842,0xbf45e403,0xbf226799,0xbf584853,0xbf08f59b,0xbf676bd8,0xbedae880,0xbf731447,0xbea09ae5,
0xbdc8bd36,0xbf7ec46d,0xbe4dee60,0xbf7ac516,0xbe9aa086,0xbf740bdd,0xbecc9b8b,0xbf6aab7b,0xbefc5d27,0xbf5ebe05,0xbf14b039,0xbf5064af,0xbf299415,0xbf3fc767,0xbf3ca003,0xbf2d1469,
0xbef15aea,0xbf61c598,0xbf14b039,0xbf5064af,0xbf2e3bde,0xbf3b8f3b,0xbf44e3f5,0xbf239da9,0xbf584853,0xbf08f59b,0xbf6816a8,0xbed8106b,0xbf740bdd,0xbe9aa086,0xbf7bf531,0xbe354098,
0xbe47c5c2,0xbf7b14be,0xbe9aa086,0xbf740bdd,0xbecf7bca,0xbf6a09a7,0xbf00e7e4,0xbf5d2d53,0xbf187fc0,0xbf4d9f02,0xbf2e3bde,0xbf3b8f3b,0xbf41d870,0xbf273656,0xbf531849,0xbf10d3cd,
0xbf0e39da,0xbf54db31,0xbf299415,0xbf3fc767,0xbf41d870,0xbf273656,0xbf5695e5,0xbf0b9a6b,0xbf676bd8,0xbedae880,0xbf740bdd,0xbe9aa086,0xbf7c3b28,0xbe2f10a2,0xbf7fd397,0xbd16c32c,
0xbe94a031,0xbf74fa0b,0xbecc9b8b,0xbf6aab7b,0xbf00e7e4,0xbf5d2d53,0xbf19c200,0xbf4cae79,0xbf3085bb,0xbf396842,0xbf44e3f5,0xbf239da9,0xbf5695e5,0xbf0b9a6b,0xbf655e0b,0xbee363fa,
0xbf226799,0xbf45e403,0xbf3ca003,0xbf2d1469,0xbf531849,0xbf10d3cd,0xbf655e0b,0xbee363fa,0xbf731447,0xbea09ae5,0xbf7bf531,0xbe354098,0xbf7fd397,0xbd16c32c,0xbf7e9bc9,0x3dd53db9,
0xbf3504f3,0xbf3504f3,0xbf4d9f02,0xbf187fc0,0xbf61c598,0xbef15aea,0xbf710908,0xbeac7cd4,0xbf7b14be,0xbe47c5c2,0xbf7fb10f,0xbd48fb30,0xbf7ec46d,0x3dc8bd36,0xbf7853f8,0x3e78cfcc,
0xbf6c835e,0xbec3ef15,0xbf79c79d,0xbe605c13,0xbf7fb10f,0xbd48fb30,0xbf7e1324,0x3dfab273,0xbf74fa0b,0x3e94a031,0xbf64aa59,0x3ee63375,0xbf4d9f02,0x3f187fc0,0xbf3085bb,0x3f396842,
0xbf45e403,0xbf226799,0xbf5c61c7,0xbf0242b1,0xbf6db293,0xbebe1d4a,0xbf796e4e,0xbe667c66,0xbf7f4e6d,0xbd96a905,0xbf7f2f9d,0x3da3308c,0xbf791298,0x3e6c9a7f,0xbf6d1c1d,0x3ec1071e,
0xbf74fa0b,0xbe94a031,0xbf7e4323,0xbdee3876,0xbf7f84ab,0x3d7b2b74,0xbf78b47b,0x3e72b651,0xbf6a09a7,0x3ecf7bca,0xbf53fac3,0x3f0f8784,0xbf373a23,0x3f32c8c9,0xbf14b039,0x3f5064af,
0xbf54db31,0xbf0e39da,0xbf68bf3c,0xbed53641,0xbf76ba07,0xbe888e93,0xbf7e70b0,0xbde1bc2e,0xbf7fb10f,0x3d48fb30,0xbf7a7302,0x3e541501,0xbf6ed89e,0x3eb8442a,0xbf5d2d53,0x3f00e7e4,
0xbf7b14be,0xbe47c5c2,0xbf7ffb11,0xbc490e90,0xbf7c3b28,0x3e2f10a2,0xbf6ff573,0x3eb263ef,0xbf5b941a,0x3f039c3d,0xbf3fc767,0x3f299415,0xbf1d7fd1,0x3f49d112,0xbeebcbbb,0x3f633c5a,
0xbf61c598,0xbef15aea,0xbf7294f8,0xbea395c5,0xbf7cbfc9,0xbe22abb6,0xbf7ffec4,0x3bc90f88,0xbf7c3b28,0x3e2f10a2,0xbf718f57,0x3ea986c4,0xbf604621,0x3ef6e0cb,0xbf48d8b3,0x3f1ebc12,
0xbf7ec46d,0xbdc8bd36,0xbf7eea9d,0x3dbc3ac3,0xbf75dec6,0x3e8e9a22,0xbf63f473,0x3ee900b7,0xbf49d112,0x3f1d7fd1,0xbf286605,0x3f40d0da,0xbf00e7e4,0x3f5d2d53,0xbea986c4,0x3f718f57,
0x3f800000,0x0,0x3f800000,0x0,0x3f800000,0x0,0x3f800000,0x0,0x3f800000,0x0,0x3f800000,0x0,0x3f800000,0x0,0x3f800000,0x0,
0x3f54db31,0xbf0e39da,0x3f514d3d,0xbf13682a,0x3f4d9f02,0xbf187fc0,0x3f49d112,0xbf1d7fd1,0x3f45e403,0xbf226799,0x3f41d870,0xbf273656,0x3f3daef9,0xbf2beb4a,0x3f396842,0xbf3085bb,
0x3f7d3aac,0xbe164083,0x3f7cfe73,0xbe1c76de,0x3f7cbfc9,0xbe22abb6,0x3f7c7eb0,0xbe28defc,0x3f7c3b28,0xbe2f10a2,0x3f7bf531,0xbe354098,0x3f7baccd,0xbe3b6ecf,0x3f7b61fc,0xbe419b37,
0x3f3daef9,0xbf2beb4a,0x3f385216,0xbf31a81d,0x3f32c8c9,0xbf373a23,0x3f2d1469,0xbf3ca003,0x3f273656,0xbf41d870,0x3f212ff9,0xbf46e22a,0x3f1b02c6,0xbf4bbbf8,0x3f14b039,0xbf5064af,
0x3f74fa0b,0xbe94a031,0x3f740bdd,0xbe9aa086,0x3f731447,0xbea09ae5,0x3f721352,0xbea68f12,0x3f710908,0xbeac7cd4,0x3f6ff573,0xbeb263ef,0x3f6ed89e,0xbeb8442a,0x3f6db293,0xbebe1d4a,
0x3f226799,0xbf45e403,0x3f1b02c6,0xbf4bbbf8,0x3f13682a,0xbf514d3d,0x3f0b9a6b,0xbf5695e5,0x3f039c3d,0xbf5b941a,0x3ef6e0cb,0xbf604621,0x3ee63375,0xbf64aa59,0x3ed53641,0xbf68bf3c,
0x3f676bd8,0xbedae880,0x3f655e0b,0xbee363fa,0x3f633c5a,0xbeebcbbb,0x3f6106f2,0xbef41f07,0x3f5ebe05,0xbefc5d27,0x3f5c61c7,0xbf0242b1,0x3f59f26a,0xbf064b82,0x3f577026,0xbf0a48ad,
0x3f039c3d,0xbf5b941a,0x3ef41f07,0xbf6106f2,0x3ee0924f,0xbf660f88,0x3ecc9b8b,0xbf6aab7b,0x3eb8442a,0xbf6ed89e,0x3ea395c5,0xbf7294f8,0x3e8e9a22,0xbf75dec6,0x3e72b651,0xbf78b47b,
0x3ec3ef15,0xbf6c835e,0x3eac7cd4,0xbf710908,0x3e94a031,0xbf74fa0b,0x3e78cfcc,0xbf7853f8,0x3e47c5c2,0xbf7b14be,0x3e164083,0xbf7d3aac,0x3dc8bd36,0xbf7ec46d,0x3d48fb30,0xbf7fb10f,
0xbe47c5c2,0xbf7b14be,0xbe888e93,0xbf76ba07,0xbeac7cd4,0xbf710908,0xbecf7bca,0xbf6a09a7,0xbef15aea,0xbf61c598,0xbf08f59b,0xbf584853,0xbf187fc0,0xbf4d9f02,0xbf273656,0xbf41d870,
0x3e78cfcc,0xbf7853f8,0x3e419b37,0xbf7b61fc,0x3e09cf86,0xbf7dabcc,0x3da3308c,0xbf7f2f9d,0x3cc90ab0,0xbf7fec43,0xbcfb49ba,0xbf7fe129,0xbdafb680,0xbf7f0e58,0xbe1008b7,0xbf7d7474,
0xbeac7cd4,0xbf710908,0xbed25a09,0xbf696591,0xbef6e0cb,0xbf604621,0xbf0cead0,0xbf55b993,0xbf1d7fd1,0xbf49d112,0xbf2d1469,0xbf3ca003,0xbf3b8f3b,0xbf2e3bde,0xbf48d8b3,0xbf1ebc12,
0x3dc8bd36,0xbf7ec46d,0x3d16c32c,0xbf7fd397,0xbcc90ab0,0xbf7fec43,0xbdafb680,0xbf7f0e58,0xbe164083,0xbf7d3aac,0xbe541501,0xbf7a7302,0xbe888e93,0xbf76ba07,0xbea68f12,0xbf721352,
0xbef15aea,0xbf61c598,0xbf0b9a6b,0xbf5695e5,0xbf1d7fd1,0xbf49d112,0xbf2e3bde,0xbf3b8f3b,0xbf3daef9,0xbf2beb4a,0xbf4bbbf8,0xbf1b02c6,0xbf584853,0xbf08f59b,0xbf633c5a,0xbeebcbbb,
0xbd48fb30,0xbf7fb10f,0xbdee3876,0xbf7e4323,0xbe3b6ecf,0xbf7baccd,0xbe7ee6e1,0xbf77f110,0xbea09ae5,0xbf731447,0xbec1071e,0xbf6d1c1d,0xbee0924f,0xbf660f88,0xbeff17b2,0xbf5df6be,
0xbf187fc0,0xbf4d9f02,0xbf2ac082,0xbf3ebc1b,0xbf3b8f3b,0xbf2e3bde,0xbf4ac77f,0xbf1c420c,0xbf584853,0xbf08f59b,0xbf63f473,0xbee900b7,0xbf6db293,0xbebe1d4a,0xbf756d97,0xbe919ddd,
0xbf3504f3,0xbf3504f3,0xbf45e403,0xbf226799,0xbf54db31,0xbf0e39da,0xbf61c598,0xbef15aea,0xbf6c835e,0xbec3ef15,0xbf74fa0b,0xbe94a031,0xbf7b14be,0xbe47c5c2,0xbf7ec46d,0xbdc8bd36,
0xbf7b14be,0xbe47c5c2,0xbf7f4e6d,0xbd96a905,0xbf7fb10f,0x3d48fb30,0xbf7c3b28,0x3e2f10a2,0xbf74fa0b,0x3e94a031,0xbf6a09a7,0x3ecf7bca,0xbf5b941a,0x3f039c3d,0xbf49d112,0x3f1d7fd1,
0xbf4d9f02,0xbf187fc0,0xbf5c61c7,0xbf0242b1,0xbf68bf3c,0xbed53641,0xbf7294f8,0xbea395c5,0xbf79c79d,0xbe605c13,0xbf7e4323,0xbdee3876,0xbf7ffb11,0xbc490e90,0xbf7eea9d,0x3dbc3ac3,
0xbf7fb10f,0xbd48fb30,0xbf7f2f9d,0x3da3308c,0xbf7a7302,0x3e541501,0xbf718f57,0x3ea986c4,0xbf64aa59,0x3ee63375,0xbf53fac3,0x3f0f8784,0xbf3fc767,0x3f299415,0xbf286605,0x3f40d0da,
0xbf61c598,0xbef15aea,0xbf6db293,0xbebe1d4a,0xbf76ba07,0xbe888e93,0xbf7cbfc9,0xbe22abb6,0xbf7fb10f,0xbd48fb30,0xbf7f84ab,0x3d7b2b74,0xbf7c3b28,0x3e2f10a2,0xbf75dec6,0x3e8e9a22,
0xbf7ec46d,0x3dc8bd36,0xbf791298,0x3e6c9a7f,0xbf6ed89e,0x3eb8442a,0xbf604621,0x3ef6e0cb,0xbf4d9f02,0x3f187fc0,0xbf373a23,0x3f32c8c9,0xbf1d7fd1,0x3f49d112,0xbf00e7e4,0x3f5d2d53,
0xbf710908,0xbeac7cd4,0xbf796e4e,0xbe667c66,0xbf7e70b0,0xbde1bc2e,0xbf7ffec4,0x3bc90f88,0xbf7e1324,0x3dfab273,0xbf78b47b,0x3e72b651,0xbf6ff573,0x3eb263ef,0xbf63f473,0x3ee900b7,
0xbf7853f8,0x3e78cfcc,0xbf6d1c1d,0x3ec1071e,0xbf5d2d53,0x3f00e7e4,0xbf48d8b3,0x3f1ebc12,0xbf3085bb,0x3f396842,0xbf14b039,0x3f5064af,0xbeebcbbb,0x3f633c5a,0xbea986c4,0x3f718f57,
0xbf6c835e,0x3ec3ef15,0xbf5b941a,0x3f039c3d,0xbf45e403,0x3f226799,0xbf2beb4a,0x3f3daef9,0xbf0e39da,0x3f54db31,0xbedae880,0x3f676bd8,0xbe94a031,0x3f74fa0b,0xbe164083,0x3f7d3aac,
0xbf0e39da,0x3f54db31,0xbecf7bca,0x3f6a09a7,0xbe78cfcc,0x3f7853f8,0xbd96a905,0x3f7f4e6d,0x3dc8bd36,0x3f7ec46d,0x3e888e93,0x3f76ba07,0x3edae880,0x3f676bd8,0x3f13682a,0x3f514d3d,
0xbf5b941a,0x3f039c3d,0xbf44e3f5,0x3f239da9,0xbf299415,0x3f3fc767,0xbf0a48ad,0x3f577026,0xbecf7bca,0x3f6a09a7,0xbe8586ce,0x3f772417,0xbde1bc2e,0x3f7e70b0,0x3d2fe007,0x3f7fc38f,
0xbedae880,0x3f676bd8,0xbe8586ce,0x3f772417,0xbdafb680,0x3f7f0e58,0x3dbc3ac3,0x3f7eea9d,0x3e888e93,0x3f76ba07,0x3eddbe79,0x3f66becc,0x3f15f6d9,0x3f4f7a1f,0x3f385216,0x3f31a81d,
0xbf45e403,0x3f226799,0xbf299415,0x3f3fc767,0xbf08f59b,0x3f584853,0xbec9b953,0x3f6b4b0c,0xbe78cfcc,0x3f7853f8,0xbdafb680,0x3f7f0e58,0x3d96a905,0x3f7f4e6d,0x3e6c9a7f,0x3f791298,
0xbe94a031,0x3f74fa0b,0xbde1bc2e,0x3f7e70b0,0x3d96a905,0x3f7f4e6d,0x3e827dc0,0x3f778bc5,0x3edae880,0x3f676bd8,0x3f15f6d9,0x3f4f7a1f,0x3f396842,0x3f3085bb,0x3f5695e5,0x3f0b9a6b,
0xbf2beb4a,0x3f3daef9,0xbf0a48ad,0x3f577026,0xbec9b953,0x3f6b4b0c,0xbe72b651,0x3f78b47b,0xbd96a905,0x3f7f4e6d,0x3dbc3ac3,0x3f7eea9d,0x3e827dc0,0x3f778bc5,0x3ed25a09,0x3f696591,
0xbe164083,0x3f7d3aac,0x3d2fe007,0x3f7fc38f,0x3e6c9a7f,0x3f791298,0x3ed25a09,0x3f696591,0x3f13682a,0x3f514d3d,0x3f385216,0x3f31a81d,0x3f5695e5,0x3f0b9a6b,0x3f6d1c1d,0x3ec1071e,
0x3e00,0x3e00,0x3e00,0x3e00,0x3e00,0x3e00,0x3e00,0x3e00,0x3e00,0x3e00,0x3e00,0x3e00,0x3e00,0x3e00,0x3e00,0x3e00,
0xbd443ded,0xbcc83dfb,0xbc493dff,0xbd153df5,0xbdb53db5,0xbdd53d8e,0xbdc63da2,0xbde23d71,0xbe000000,0xbdfbbcc8,0xbdffbc49,0xbdf5bd15,0xbdb5bdb5,0xbd8ebdd5,0xbda2bdc6,0xbd71bde2,
0xbdb53db5,0xbd443ded,0xbcc83dfb,0xbd8e3dd5,0xbe000000,0xbdedbd44,0xbdfbbcc8,0xbdd5bd8e,0xbe00,0x3d44bded,0x3cc8bdfb,0x3d8ebdd5,0x3e000000,0x3ded3d44,0x3dfb3cc8,0x3dd53d8e,
0xbded3d44,0xbd8e3dd5,0xbd153df5,0xbdc63da2,0xbdb5bdb5,0xbcc8bdfb,0xbd71bde2,0x3c49bdff,0x3e000000,0x3dd53d8e,0x3df53d15,0x3da23dc6,0xbdb53db5,0xbdfb3cc8,0xbde23d71,0xbdffbc49,
0xbe000000,0xbdb53db5,0xbd443ded,0xbded3d44,0xbe00,0x3db5bdb5,0x3d44bded,0x3dedbd44,0x3e00,0xbdb53db5,0xbd443ded,0xbded3d44,0xbe00,0x3db5bdb5,0x3d44bded,0x3dedbd44,
0xbdedbd44,0xbdd53d8e,0xbd713de2,0xbdff3c49,0x3db5bdb5,0x3dfb3cc8,0x3df5bd15,0x3dc63da2,0xbe000000,0xbd8ebdd5,0xbde2bd71,0xbc49bdff,0x3db53db5,0xbcc83dfb,0x3d153df5,0xbda23dc6,
0xbdb5bdb5,0xbded3d44,0xbd8e3dd5,0xbdfbbcc8,0x3e000000,0x3d443ded,0x3dd53d8e,0xbcc83dfb,0xbe00,0x3dedbd44,0x3d8ebdd5,0x3dfb3cc8,0xbe000000,0xbd44bded,0xbdd5bd8e,0x3cc8bdfb,
0xbd44bded,0xbdfb3cc8,0xbda23dc6,0xbde2bd71,0x3db53db5,0xbd8e3dd5,0x3c493dff,0xbdf53d15,0x3e000000,0x3cc83dfb,0x3dc63da2,0xbd713de2,0x3db5bdb5,0x3dd53d8e,0x3dffbc49,0x3d153df5,
0xbe00,0xbe000000,0xbdb53db5,0xbdb5bdb5,0x3e00,0xbe000000,0xbdb53db5,0xbdb5bdb5,0x3e00,0xbe000000,0xbdb53db5,0xbdb5bdb5,0x3e00,0xbe000000,0xbdb53db5,0xbdb5bdb5,
0x3d44bded,0xbdfbbcc8,0xbdc63da2,0xbd71bde2,0xbdb53db5,0xbd8ebdd5,0xbdffbc49,0x3d15bdf5,0xbe000000,0x3cc8bdfb,0xbda2bdc6,0x3de2bd71,0xbdb5bdb5,0x3dd5bd8e,0x3c49bdff,0x3df53d15,
0x3db5bdb5,0xbdedbd44,0xbdd53d8e,0xbcc8bdfb,0xbe000000,0x3d44bded,0xbd8ebdd5,0x3dfbbcc8,0xbe00,0x3ded3d44,0x3dd5bd8e,0x3cc83dfb,0x3e000000,0xbd443ded,0x3d8e3dd5,0xbdfb3cc8,
0x3dedbd44,0xbdd5bd8e,0xbde23d71,0x3c49bdff,0xbdb5bdb5,0x3dfbbcc8,0x3d15bdf5,0x3da23dc6,0x3e000000,0xbd8e3dd5,0x3d713de2,0xbdffbc49,0xbdb53db5,0xbcc8bdfb,0xbdf5bd15,0x3dc6bda2,
0x3e000000,0xbdb5bdb5,0xbded3d44,0x3d44bded,0xbe00,0x3db53db5,0x3dedbd44,0xbd443ded,0x3e00,0xbdb5bdb5,0xbded3d44,0x3d44bded,0xbe00,0x3db53db5,0x3dedbd44,0xbd443ded,
0x3ded3d44,0xbd8ebdd5,0xbdf53d15,0x3da2bdc6,0x3db5bdb5,0xbcc83dfb,0x3de23d71,0xbdff3c49,0xbe000000,0x3dd5bd8e,0xbd15bdf5,0x3dc63da2,0x3db53db5,0xbdfbbcc8,0xbd713de2,0xbc49bdff,
0x3db53db5,0xbd44bded,0xbdfb3cc8,0x3dd5bd8e,0x3e000000,0xbded3d44,0x3cc83dfb,0xbd8ebdd5,0xbe00,0x3d443ded,0x3dfbbcc8,0xbdd53d8e,0xbe000000,0x3dedbd44,0xbcc8bdfb,0x3d8e3dd5,
0x3d443ded,0xbcc8bdfb,0xbdff3c49,0x3df5bd15,0x3db53db5,0xbdd5bd8e,0xbda23dc6,0x3d71bde2,0x3e000000,0xbdfb3cc8,0x3c493dff,0xbd15bdf5,0x3db5bdb5,0xbd8e3dd5,0x3dc63da2,0xbde2bd71,
0x3e00,0xbe00,0xbe000000,0x3e000000,0x3e00,0xbe00,0xbe000000,0x3e000000,0x3e00,0xbe00,0xbe000000,0x3e000000,0x3e00,0xbe00,0xbe000000,0x3e000000,
0xbd443ded,0x3cc8bdfb,0xbdffbc49,0x3df53d15,0xbdb53db5,0x3dd5bd8e,0xbda2bdc6,0x3d713de2,0xbe000000,0x3dfb3cc8,0x3c49bdff,0xbd153df5,0xbdb5bdb5,0x3d8e3dd5,0x3dc6bda2,0xbde23d71,
0xbdb53db5,0x3d44bded,0xbdfbbcc8,0x3dd53d8e,0xbe000000,0x3ded3d44,0x3cc8bdfb,0xbd8e3dd5,0xbe00,0xbd443ded,0x3dfb3cc8,0xbdd5bd8e,0x3e000000,0xbdedbd44,0xbcc83dfb,0x3d8ebdd5,
0xbded3d44,0x3d8ebdd5,0xbdf5bd15,0x3da23dc6,0xbdb5bdb5,0x3cc83dfb,0x3de2bd71,0xbdffbc49,0x3e000000,0xbdd5bd8e,0xbd153df5,0x3dc6bda2,0xbdb53db5,0x3dfbbcc8,0xbd71bde2,0xbc493dff,
0xbe000000,0x3db5bdb5,0xbdedbd44,0x3d443ded,0xbe00,0xbdb53db5,0x3ded3d44,0xbd44bded,0x3e00,0x3db5bdb5,0xbdedbd44,0x3d443ded,0xbe00,0xbdb53db5,0x3ded3d44,0xbd44bded,
0xbdedbd44,0x3dd5bd8e,0xbde2bd71,0x3c493dff,0x3db5bdb5,0xbdfbbcc8,0x3d153df5,0x3da2bdc6,0xbe000000,0x3d8e3dd5,0x3d71bde2,0xbdff3c49,0x3db53db5,0x3cc8bdfb,0xbdf53d15,0x3dc63da2,
0xbdb5bdb5,0x3dedbd44,0xbdd5bd8e,0xbcc83dfb,0x3e000000,0xbd44bded,0xbd8e3dd5,0x3dfb3cc8,0xbe00,0xbded3d44,0x3dd53d8e,0x3cc8bdfb,0xbe000000,0x3d443ded,0x3d8ebdd5,0xbdfbbcc8,
0xbd44bded,0x3dfbbcc8,0xbdc6bda2,0xbd713de2,0x3db53db5,0x3d8ebdd5,0xbdff3c49,0x3d153df5,0x3e000000,0xbcc8bdfb,0xbda23dc6,0x3de23d71,0x3db5bdb5,0xbdd5bd8e,0x3c493dff,0x3df5bd15,
0xbe00,0x3e000000,0xbdb5bdb5,0xbdb53db5,0x3e00,0x3e000000,0xbdb5bdb5,0xbdb53db5,0x3e00,0x3e000000,0xbdb5bdb5,0xbdb53db5,0x3e00,0x3e000000,0xbdb5bdb5,0xbdb53db5,
0x3d44bded,0x3dfb3cc8,0xbda2bdc6,0xbde23d71,0xbdb53db5,0x3d8e3dd5,0x3c49bdff,0xbdf5bd15,0xbe000000,0xbcc83dfb,0x3dc6bda2,0xbd71bde2,0xbdb5bdb5,0xbdd53d8e,0x3dff3c49,0x3d15bdf5,
0x3db5bdb5,0x3ded3d44,0xbd8ebdd5,0xbdfb3cc8,0xbe000000,0xbd443ded,0x3dd5bd8e,0xbcc8bdfb,0xbe00,0xbdedbd44,0x3d8e3dd5,0x3dfbbcc8,0x3e000000,0x3d44bded,0xbdd53d8e,0x3cc83dfb,
0x3dedbd44,0x3dd53d8e,0xbd71bde2,0xbdffbc49,0xbdb5bdb5,0xbdfb3cc8,0x3df53d15,0x3dc6bda2,0x3e000000,0x3d8ebdd5,0xbde23d71,0xbc493dff,0xbdb53db5,0x3cc83dfb,0x3d15bdf5,0xbda2bdc6,
0x3e000000,0x3db53db5,0xbd44bded,0xbdedbd44,0xbe00,0xbdb5bdb5,0x3d443ded,0x3ded3d44,0x3e00,0x3db53db5,0xbd44bded,0xbdedbd44,0xbe00,0xbdb5bdb5,0x3d443ded,0x3ded3d44,
0x3ded3d44,0x3d8e3dd5,0xbd15bdf5,0xbdc6bda2,0x3db5bdb5,0x3cc8bdfb,0xbd713de2,0x3c493dff,0xbe000000,0xbdd53d8e,0x3df5bd15,0x3da2bdc6,0x3db53db5,0x3dfb3cc8,0xbde2bd71,0xbdff3c49,
0x3db53db5,0x3d443ded,0xbcc8bdfb,0xbd8ebdd5,0x3e000000,0x3dedbd44,0xbdfb3cc8,0xbdd53d8e,0xbe00,0xbd44bded,0x3cc83dfb,0x3d8e3dd5,0xbe000000,0xbded3d44,0x3dfbbcc8,0x3dd5bd8e,
0x3d443ded,0x3cc83dfb,0xbc49bdff,0xbd15bdf5,0x3db53db5,0x3dd53d8e,0xbdc6bda2,0xbde2bd71,0x3e000000,0x3dfbbcc8,0xbdff3c49,0xbdf53d15,0x3db5bdb5,0x3d8ebdd5,0xbda23dc6,0xbd713de2,
0x3d803d80,0x3e00,0x3e00,0x3e00,0x3e00,0x3e00,0x3e00,0x3e00,0x3e00,0x3e00,0x3e00,0x3e00,0x3e00,0x3e00,0x3e00,0x3e00,
0xbd803d80,0x3cc8bdfb,0x3c49bdff,0x3d15bdf5,0xbded3d44,0x3dd5bd8e,0x3dc6bda2,0x3de2bd71,0xbdedbd44,0x3dfb3cc8,0x3dff3c49,0x3df53d15,0xbd44bded,0x3d8e3dd5,0x3da23dc6,0x3d713de2,
0x3d803d80,0xbd443ded,0xbcc83dfb,0xbd8e3dd5,0xbdb5bdb5,0xbdedbd44,0xbdfbbcc8,0xbdd5bd8e,0x3db5bdb5,0x3d44bded,0x3cc8bdfb,0x3d8ebdd5,0x3db53db5,0x3ded3d44,0x3dfb3cc8,0x3dd53d8e,
0xbd803d80,0x3d8ebdd5,0x3d15bdf5,0x3dc6bda2,0x3d44bded,0x3cc83dfb,0x3d713de2,0xbc493dff,0x3d443ded,0xbdd5bd8e,0xbdf5bd15,0xbda2bdc6,0xbdedbd44,0x3dfbbcc8,0x3de2bd71,0x3dff3c49,
0x3d803d80,0xbdb53db5,0xbd443ded,0xbded3d44,0x3e000000,0x3db5bdb5,0x3d44bded,0x3dedbd44,0xbe000000,0xbdb53db5,0xbd443ded,0xbded3d44,0x3e000000,0x3db5bdb5,0x3d44bded,0x3dedbd44,
0xbd803d80,0x3dd5bd8e,0x3d71bde2,0x3dffbc49,0x3d443ded,0xbdfbbcc8,0xbdf53d15,0xbdc6bda2,0x3d44bded,0x3d8e3dd5,0x3de23d71,0x3c493dff,0xbded3d44,0x3cc8bdfb,0xbd15bdf5,0x3da2bdc6,
0x3d803d80,0xbded3d44,0xbd8e3dd5,0xbdfbbcc8,0xbdb53db5,0x3d443ded,0x3dd53d8e,0xbcc83dfb,0x3db53db5,0x3dedbd44,0x3d8ebdd5,0x3dfb3cc8,0x3db5bdb5,0xbd44bded,0xbdd5bd8e,0x3cc8bdfb,
0xbd803d80,0x3dfbbcc8,0x3da2bdc6,0x3de23d71,0xbdedbd44,0x3d8ebdd5,0xbc49bdff,0x3df5bd15,0xbded3d44,0xbcc8bdfb,0xbdc6bda2,0x3d71bde2,0xbd443ded,0xbdd5bd8e,0xbdff3c49,0xbd15bdf5,
0x3d803d80,0xbe000000,0xbdb53db5,0xbdb5bdb5,0xbe00,0xbe000000,0xbdb53db5,0xbdb5bdb5,0xbe00,0xbe000000,0xbdb53db5,0xbdb5bdb5,0xbe00,0xbe000000,0xbdb53db5,0xbdb5bdb5,
0xbd803d80,0x3dfb3cc8,0x3dc6bda2,0x3d713de2,0x3dedbd44,0x3d8e3dd5,0x3dff3c49,0xbd153df5,0x3ded3d44,0xbcc83dfb,0x3da23dc6,0xbde23d71,0x3d443ded,0xbdd53d8e,0xbc493dff,0xbdf5bd15,
0x3d803d80,0xbdedbd44,0xbdd53d8e,0xbcc8bdfb,0x3db53db5,0x3d44bded,0xbd8ebdd5,0x3dfbbcc8,0xbdb53db5,0x3ded3d44,0x3dd5bd8e,0x3cc83dfb,0xbdb5bdb5,0xbd443ded,0x3d8e3dd5,0xbdfb3cc8,
0xbd803d80,0x3dd53d8e,0x3de2bd71,0xbc493dff,0xbd443ded,0xbdfb3cc8,0xbd153df5,0xbda2bdc6,0xbd44bded,0x3d8ebdd5,0xbd71bde2,0x3dff3c49,0x3ded3d44,0x3cc83dfb,0x3df53d15,0xbdc63da2,
0x3d803d80,0xbdb5bdb5,0xbded3d44,0x3d44bded,0xbe000000,0x3db53db5,0x3dedbd44,0xbd443ded,0x3e000000,0xbdb5bdb5,0xbded3d44,0x3d44bded,0xbe000000,0x3db53db5,0x3dedbd44,0xbd443ded,
0xbd803d80,0x3d8e3dd5,0x3df5bd15,0xbda23dc6,0xbd44bded,0x3cc8bdfb,0xbde2bd71,0x3dffbc49,0xbd443ded,0xbdd53d8e,0x3d153df5,0xbdc6bda2,0x3dedbd44,0x3dfb3cc8,0x3d71bde2,0x3c493dff,
0x3d803d80,0xbd44bded,0xbdfb3cc8,0x3dd5bd8e,0x3db5bdb5,0xbded3d44,0x3cc83dfb,0xbd8ebdd5,0xbdb5bdb5,0x3d443ded,0x3dfbbcc8,0xbdd53d8e,0xbdb53db5,0x3dedbd44,0xbcc8bdfb,0x3d8e3dd5,
0xbd803d80,0x3cc83dfb,0x3dffbc49,0xbdf53d15,0x3ded3d44,0x3dd53d8e,0x3da2bdc6,0xbd713de2,0x3dedbd44,0x3dfbbcc8,0xbc49bdff,0x3d153df5,0x3d44bded,0x3d8ebdd5,0xbdc6bda2,0x3de23d71,
0x3d803d80,0xbe00,0xbe000000,0x3e000000,0x3e00,0xbe00,0xbe000000,0x3e000000,0x3e00,0xbe00,0xbe000000,0x3e000000,0x3e00,0xbe00,0xbe000000,0x3e000000,
0xbd803d80,0xbcc83dfb,0x3dff3c49,0xbdf5bd15,0xbded3d44,0xbdd53d8e,0x3da23dc6,0xbd71bde2,0xbdedbd44,0xbdfbbcc8,0xbc493dff,0x3d15bdf5,0xbd44bded,0xbd8ebdd5,0xbdc63da2,0x3de2bd71,
0x3d803d80,0x3d44bded,0xbdfbbcc8,0x3dd53d8e,0xbdb5bdb5,0x3ded3d44,0x3cc8bdfb,0xbd8e3dd5,0x3db5bdb5,0xbd443ded,0x3dfb3cc8,0xbdd5bd8e,0x3db53db5,0xbdedbd44,0xbcc83dfb,0x3d8ebdd5,
0xbd803d80,0xbd8e3dd5,0x3df53d15,0xbda2bdc6,0x3d44bded,0xbcc8bdfb,0xbde23d71,0x3dff3c49,0x3d443ded,0x3dd53d8e,0x3d15bdf5,0xbdc63da2,0xbdedbd44,0xbdfb3cc8,0x3d713de2,0x3c49bdff,
0x3d803d80,0x3db5bdb5,0xbdedbd44,0x3d443ded,0x3e000000,0xbdb53db5,0x3ded3d44,0xbd44bded,0xbe000000,0x3db5bdb5,0xbdedbd44,0x3d443ded,0x3e000000,0xbdb53db5,0x3ded3d44,0xbd44bded,
0xbd803d80,0xbdd53d8e,0x3de23d71,0xbc49bdff,0x3d443ded,0x3dfb3cc8,0xbd15bdf5,0xbda23dc6,0x3d44bded,0xbd8ebdd5,0xbd713de2,0x3dffbc49,0xbded3d44,0xbcc83dfb,0x3df5bd15,0xbdc6bda2,
0x3d803d80,0x3dedbd44,0xbdd5bd8e,0xbcc83dfb,0xbdb53db5,0xbd44bded,0xbd8e3dd5,0x3dfb3cc8,0x3db53db5,0xbded3d44,0x3dd53d8e,0x3cc8bdfb,0x3db5bdb5,0x3d443ded,0x3d8ebdd5,0xbdfbbcc8,
0xbd803d80,0xbdfb3cc8,0x3dc63da2,0x3d71bde2,0xbdedbd44,0xbd8e3dd5,0x3dffbc49,0xbd15bdf5,0xbded3d44,0x3cc83dfb,0x3da2bdc6,0xbde2bd71,0xbd443ded,0x3dd53d8e,0xbc49bdff,0xbdf53d15,
0x3d803d80,0x3e000000,0xbdb5bdb5,0xbdb53db5,0xbe00,0x3e000000,0xbdb5bdb5,0xbdb53db5,0xbe00,0x3e000000,0xbdb5bdb5,0xbdb53db5,0xbe00,0x3e000000,0xbdb5bdb5,0xbdb53db5,
0xbd803d80,0xbdfbbcc8,0x3da23dc6,0x3de2bd71,0x3dedbd44,0xbd8ebdd5,0xbc493dff,0x3df53d15,0x3ded3d44,0x3cc8bdfb,0xbdc63da2,0x3d713de2,0x3d443ded,0x3dd5bd8e,0xbdffbc49,0xbd153df5,
0x3d803d80,0x3ded3d44,0xbd8ebdd5,0xbdfb3cc8,0x3db53db5,0xbd443ded,0x3dd5bd8e,0xbcc8bdfb,0xbdb53db5,0xbdedbd44,0x3d8e3dd5,0x3dfbbcc8,0xbdb5bdb5,0x3d44bded,0xbdd53d8e,0x3cc83dfb,
0xbd803d80,0xbdd5bd8e,0x3d713de2,0x3dff3c49,0xbd443ded,0x3dfbbcc8,0xbdf5bd15,0xbdc63da2,0xbd44bded,0xbd8e3dd5,0x3de2bd71,0x3c49bdff,0x3ded3d44,0xbcc8bdfb,0xbd153df5,0x3da23dc6,
0x3d803d80,0x3db53db5,0xbd44bded,0xbdedbd44,0xbe000000,0xbdb5bdb5,0x3d443ded,0x3ded3d44,0x3e000000,0x3db53db5,0xbd44bded,0xbdedbd44,0xbe000000,0xbdb5bdb5,0x3d443ded,0x3ded3d44,
0xbd803d80,0xbd8ebdd5,0x3d153df5,0x3dc63da2,0xbd44bded,0xbcc83dfb,0x3d71bde2,0xbc49bdff,0xbd443ded,0x3dd5bd8e,0xbdf53d15,0xbda23dc6,0x3dedbd44,0xbdfbbcc8,0x3de23d71,0x3dffbc49,
0x3d803d80,0x3d443ded,0xbcc8bdfb,0xbd8ebdd5,0x3db5bdb5,0x3dedbd44,0xbdfb3cc8,0xbdd53d8e,0xbdb5bdb5,0xbd44bded,0x3cc83dfb,0x3d8e3dd5,0xbdb53db5,0xbded3d44,0x3dfbbcc8,0x3dd5bd8e,
0xbd803d80,0xbcc8bdfb,0x3c493dff,0x3d153df5,0x3ded3d44,0xbdd5bd8e,0x3dc63da2,0x3de23d71,0x3dedbd44,0xbdfb3cc8,0x3dffbc49,0x3df5bd15,0x3d44bded,0xbd8e3dd5,0x3da2bdc6,0x3d71bde2,
0xbc493dff,0xbbc93e00,0xbb493e00,0xbc173dff,0xbcc83dfb,0xbcf93df8,0xbce03dfa,0xbd093df7,0xbd443ded,0xbd5b3de7,0xbd4f3dea,0xbd663de5,0xbd8e3dd5,0xbd983dce,0xbd933dd1,0xbd9d3dca,
0xbd713de2,0xbcf93df8,0xbc7b3dfe,0xbd383def,0xbdd53d8e,0xbdf13d2c,0xbde53d66,0xbdfa3ce0,0xbdedbd44,0xbdcebd98,0xbddfbd7c,0xbdb9bdb1,0xbcc8bdfb,0x3bc9be00,0xbc17bdff,0x3cafbdfc,
0xbdc63da2,0xbd5b3de7,0xbce03dfa,0xbd9d3dca,0xbdfbbcc8,0xbdcebd98,0xbdeabd4f,0xbda7bdc2,0x3d44bded,0x3dbebdac,0x3d93bdd1,0x3ddfbd7c,0x3dd53d8e,0x3d843ddc,0x3db13db9,0x3d213df3,
0xbdf53d15,0xbd983dce,0xbd213df3,0xbdd13d93,0xbd8ebdd5,0x3bc9be00,0xbd09bdf7,0x3d38bdef,0x3ded3d44,0x3d843ddc,0x3dc23da7,0x3ce03dfa,0xbdfb3cc8,0xbde7bd5b,0xbdfebc7b,0xbdb9bdb1,
0xbdffbc49,0xbdbe3dac,0xbd4f3dea,0xbdf33d21,0x3cc8bdfb,0x3ddcbd84,0x3d93bdd1,0x3dfebc7b,0xbd443ded,0xbdf13d2c,0xbdb93db1,0xbdffbc17,0x3d8ebdd5,0x3dfdbc96,0x3dd8bd89,0x3df73d09,
0xbde2bd71,0xbddc3d84,0xbd7c3ddf,0xbe003b49,0x3dd5bd8e,0x3de73d5b,0x3dffbc17,0x3d933dd1,0xbdedbd44,0xbc96bdfd,0xbd9dbdca,0x3d38bdef,0x3cc83dfb,0xbdbe3dac,0xbd213df3,0xbdfa3ce0,
0xbda2bdc6,0xbdf13d2c,0xbd933dd1,0xbdf7bd09,0x3dfb3cc8,0x3c963dfd,0x3db13db9,0xbd663de5,0x3d44bded,0x3e003bc9,0x3dd8bd89,0x3dca3d9d,0xbdd5bd8e,0x3cf9bdf8,0xbd38bdef,0x3dc2bda7,
0xbd15bdf5,0xbdfd3c96,0xbda73dc2,0xbdd8bd89,0x3d8e3dd5,0xbdbe3dac,0xbc7b3dfe,0xbe003b49,0x3ded3d44,0xbcf93df8,0x3d663de5,0xbdd13d93,0x3dfbbcc8,0x3d2c3df1,0x3ddf3d7c,0xbd383def,
0x3c49bdff,0xbe00bbc9,0xbdb93db1,0xbda7bdc2,0xbcc83dfb,0xbdf8bcf9,0xbdd83d89,0xbd7cbddf,0xbd443ded,0xbde7bd5b,0xbdef3d38,0xbd21bdf3,0xbd8e3dd5,0xbdcebd98,0xbdfc3caf,0xbc7bbdfe,
0x3d71bde2,0xbdf8bcf9,0xbdca3d9d,0xbd4fbdea,0xbdd53d8e,0xbd2cbdf1,0xbdf3bd21,0x3d89bdd8,0xbdedbd44,0x3d98bdce,0xbd09bdf7,0x3e00bb49,0xbcc8bdfb,0x3e003bc9,0x3da7bdc2,0x3d933dd1,
0x3dc6bda2,0xbde7bd5b,0xbdd83d89,0xbc7bbdfe,0xbdfbbcc8,0x3d98bdce,0xbd38bdef,0x3dff3c17,0x3d44bded,0x3dac3dbe,0x3dfcbcaf,0xbd093df7,0x3dd53d8e,0xbddc3d84,0xbb493e00,0xbde5bd66,
0x3df5bd15,0xbdcebd98,0xbde53d66,0x3cafbdfc,0xbd8ebdd5,0x3e003bc9,0x3d7cbddf,0x3d4f3dea,0x3ded3d44,0xbddc3d84,0x3c173dff,0xbdd8bd89,0xbdfb3cc8,0x3d5bbde7,0xbd9dbdca,0x3e00bb49,
0x3dff3c49,0xbdacbdbe,0xbdef3d38,0x3d66bde5,0x3cc8bdfb,0x3d843ddc,0x3dfcbcaf,0xbd9d3dca,0xbd443ded,0xbd2cbdf1,0xbe00bb49,0x3dc2bda7,0x3d8ebdd5,0x3c963dfd,0x3dfa3ce0,0xbddf3d7c,
0x3de23d71,0xbd84bddc,0xbdf73d09,0x3db1bdb9,0x3dd5bd8e,0xbd5b3de7,0x3dc23da7,0xbdfcbcaf,0xbdedbd44,0x3dfdbc96,0x3c7bbdfe,0x3d4f3dea,0x3cc83dfb,0xbdacbdbe,0xbde53d66,0x3d89bdd8,
0x3da23dc6,0xbd2cbdf1,0xbdfc3caf,0x3ddfbd7c,0x3dfb3cc8,0xbdfd3c96,0xbb493e00,0xbd21bdf3,0x3d44bded,0xbbc93e00,0x3dfa3ce0,0xbdfe3c7b,0xbdd5bd8e,0x3df83cf9,0x3d4fbdea,0xbc173dff,
0x3d153df5,0xbc96bdfd,0xbdff3c17,0x3dfabce0,0x3d8e3dd5,0xbdacbdbe,0xbdca3d9d,0x3db1bdb9,0x3ded3d44,0xbdf8bcf9,0xbd213df3,0x3cafbdfc,0x3dfbbcc8,0xbdf13d2c,0x3d093df7,0xbd4fbdea,
0xbc493dff,0x3bc9be00,0xbe00bb49,0x3dff3c17,0xbcc83dfb,0x3cf9bdf8,0xbdfabce0,0x3df73d09,0xbd443ded,0x3d5bbde7,0xbdeabd4f,0x3de53d66,0xbd8e3dd5,0x3d98bdce,0xbdd1bd93,0x3dca3d9d,
0xbd713de2,0x3cf9bdf8,0xbdfebc7b,0x3def3d38,0xbdd53d8e,0x3df1bd2c,0xbd66bde5,0x3ce03dfa,0xbdedbd44,0x3dce3d98,0x3d7cbddf,0xbdb13db9,0xbcc8bdfb,0xbbc93e00,0x3dffbc17,0xbdfcbcaf,
0xbdc63da2,0x3d5bbde7,0xbdfabce0,0x3dca3d9d,0xbdfbbcc8,0x3dce3d98,0x3d4fbdea,0xbdc23da7,0x3d44bded,0xbdbe3dac,0x3dd13d93,0xbd7cbddf,0x3dd53d8e,0xbd84bddc,0xbdb93db1,0x3df3bd21,
0xbdf53d15,0x3d98bdce,0xbdf3bd21,0x3d933dd1,0xbd8ebdd5,0xbbc93e00,0x3df7bd09,0xbdefbd38,0x3ded3d44,0xbd84bddc,0xbda73dc2,0x3dfabce0,0xbdfb3cc8,0x3de73d5b,0x3c7bbdfe,0xbdb13db9,
0xbdffbc49,0x3dbebdac,0xbdeabd4f,0x3d213df3,0x3cc8bdfb,0xbddc3d84,0x3dd13d93,0xbc7bbdfe,0xbd443ded,0x3df1bd2c,0xbdb1bdb9,0xbc173dff,0x3d8ebdd5,0xbdfd3c96,0x3d893dd8,0x3d09bdf7,
0xbde2bd71,0x3ddcbd84,0xbddfbd7c,0x3b493e00,0x3dd5bd8e,0xbde7bd5b,0x3c173dff,0x3dd1bd93,0xbdedbd44,0x3c963dfd,0x3dcabd9d,0xbdefbd38,0x3cc83dfb,0x3dbebdac,0xbdf3bd21,0x3ce03dfa,
0xbda2bdc6,0x3df1bd2c,0xbdd1bd93,0xbd093df7,0x3dfb3cc8,0xbc96bdfd,0xbdb93db1,0x3de53d66,0x3d44bded,0xbe00bbc9,0x3d893dd8,0x3d9dbdca,0xbdd5bd8e,0xbcf93df8,0x3defbd38,0xbda7bdc2,
0xbd15bdf5,0x3dfdbc96,0xbdc2bda7,0xbd893dd8,0x3d8e3dd5,0x3dbebdac,0xbdfebc7b,0x3b493e00,0x3ded3d44,0x3cf9bdf8,0xbde53d66,0x3d933dd1,0x3dfbbcc8,0xbd2cbdf1,0xbd7c3ddf,0x3def3d38,
0x3c49bdff,0x3e003bc9,0xbdb1bdb9,0xbdc23da7,0xbcc83dfb,0x3df83cf9,0xbd89bdd8,0xbddf3d7c,0xbd443ded,0x3de73d5b,0xbd38bdef,0xbdf33d21,0xbd8e3dd5,0x3dce3d98,0xbcafbdfc,0xbdfe3c7b,
0x3d71bde2,0x3df83cf9,0xbd9dbdca,0xbdea3d4f,0xbdd53d8e,0x3d2c3df1,0x3d21bdf3,0xbdd8bd89,0xbdedbd44,0xbd983dce,0x3df7bd09,0xbb49be00,0xbcc8bdfb,0xbe00bbc9,0x3dc23da7,0x3dd1bd93,
0x3dc6bda2,0x3de73d5b,0xbd89bdd8,0xbdfe3c7b,0xbdfbbcc8,0xbd983dce,0x3defbd38,0x3c17bdff,0x3d44bded,0xbdacbdbe,0x3caf3dfc,0x3df73d09,0x3dd53d8e,0x3ddcbd84,0xbe00bb49,0xbd663de5,
0x3df5bd15,0x3dce3d98,0xbd66bde5,0xbdfcbcaf,0xbd8ebdd5,0xbe00bbc9,0x3ddf3d7c,0x3deabd4f,0x3ded3d44,0x3ddcbd84,0xbdff3c17,0xbd893dd8,0xbdfb3cc8,0xbd5b3de7,0x3dcabd9d,0xbb49be00,
0x3dff3c49,0x3dac3dbe,0xbd38bdef,0xbde5bd66,0x3cc8bdfb,0xbd84bddc,0x3caf3dfc,0x3dca3d9d,0xbd443ded,0x3d2c3df1,0x3b49be00,0xbda7bdc2,0x3d8ebdd5,0xbc96bdfd,0xbce03dfa,0x3d7c3ddf,
0x3de23d71,0x3d843ddc,0xbd09bdf7,0xbdb9bdb1,0x3dd5bd8e,0x3d5bbde7,0xbda73dc2,0xbcaf3dfc,0xbdedbd44,0xbdfd3c96,0x3dfe3c7b,0x3deabd4f,0x3cc83dfb,0x3dac3dbe,0xbd66bde5,0xbdd8bd89,
0x3da23dc6,0x3d2c3df1,0xbcafbdfc,0xbd7cbddf,0x3dfb3cc8,0x3dfdbc96,0xbe00bb49,0xbdf33d21,0x3d44bded,0x3bc9be00,0xbce03dfa,0x3c7b3dfe,0xbdd5bd8e,0xbdf8bcf9,0x3dea3d4f,0x3dff3c17,
0x3d153df5,0x3c963dfd,0xbc17bdff,0xbce0bdfa,0x3d8e3dd5,0x3dac3dbe,0xbd9dbdca,0xbdb9bdb1,0x3ded3d44,0x3df83cf9,0xbdf3bd21,0xbdfcbcaf,0x3dfbbcc8,0x3df1bd2c,0xbdf73d09,0xbdea3d4f,
0xbdb53d80,0xbdbe3dac,0xbdb93db1,0xbdc23da7,0xbd153df5,0xbddc3d84,0xbdd83d89,0xbddf3d7c,0xbd713de2,0xbdf13d2c,0xbdef3d38,0xbdf33d21,0xbda23dc6,0xbdfd3c96,0xbdfc3caf,0xbdfe3c7b,
0x3db53d80,0x3ddcbd84,0x3dcabd9d,0x3deabd4f,0xbdff3c49,0x3de73d5b,0x3df33d21,0x3dd83d89,0xbda2bdc6,0x3c963dfd,0x3d093df7,0x3b493e00,0x3d15bdf5,0xbdbe3dac,0xbda73dc2,0xbdd13d93,
0xbdb53d80,0xbdf13d2c,0xbdd83d89,0xbdfe3c7b,0xbd71bde2,0xbc96bdfd,0xbd38bdef,0x3c17bdff,0x3df5bd15,0x3e003bc9,0x3dfcbcaf,0x3df73d09,0x3c493dff,0xbcf93df8,0xbb493e00,0xbd663de5,
0x3db53d80,0x3dfdbc96,0x3de5bd66,0x3dfc3caf,0x3da2bdc6,0xbdbe3dac,0xbd7c3ddf,0xbdea3d4f,0xbc493dff,0x3cf9bdf8,0xbc17bdff,0x3d89bdd8,0xbd71bde2,0x3d2c3df1,0x3d9d3dca,0x3b493e00,
0xbdb53d80,0xbe00bbc9,0xbdef3d38,0xbde5bd66,0x3df53d15,0x3df83cf9,0x3dfcbcaf,0x3dca3d9d,0xbde2bd71,0xbde7bd5b,0xbe00bb49,0xbda7bdc2,0x3dc63da2,0x3dce3d98,0x3dfa3ce0,0x3d7c3ddf,
0x3db53d80,0x3df83cf9,0x3df7bd09,0x3db93db1,0x3c493dff,0xbd2cbdf1,0xbdc2bda7,0x3cafbdfc,0x3dc6bda2,0xbd983dce,0xbc7b3dfe,0xbdea3d4f,0xbdf5bd15,0x3e003bc9,0x3de5bd66,0x3dd83d89,
0xbdb53d80,0xbde7bd5b,0xbdfc3caf,0xbd7cbddf,0xbde23d71,0xbd983dce,0xbb493e00,0xbdf33d21,0x3d153df5,0x3dac3dbe,0x3dfa3ce0,0x3c7b3dfe,0x3dffbc49,0x3ddcbd84,0x3d4fbdea,0x3dff3c17,
0x3db53d80,0x3dce3d98,0x3dffbc17,0x3ce03dfa,0xbdc6bda2,0x3e003bc9,0x3dcabd9d,0x3db93db1,0xbdffbc49,0x3ddcbd84,0x3d21bdf3,0x3dfc3caf,0xbde23d71,0x3d5bbde7,0xbd09bdf7,0x3deabd4f,
0xbdb53d80,0xbdacbdbe,0xbe00bb49,0x3c17bdff,0x3d15bdf5,0xbd84bddc,0xbdfabce0,0x3d09bdf7,0x3d71bde2,0xbd2cbdf1,0xbdeabd4f,0x3d66bde5,0x3da2bdc6,0xbc96bdfd,0xbdd1bd93,0x3d9dbdca,
0x3db53d80,0x3d843ddc,0x3dfe3c7b,0xbd383def,0x3dffbc49,0xbd5b3de7,0x3d663de5,0xbdfa3ce0,0x3da23dc6,0xbdfd3c96,0xbd7c3ddf,0xbdb9bdb1,0xbd153df5,0xbdacbdbe,0xbdff3c17,0x3cafbdfc,
0xbdb53d80,0xbd2cbdf1,0xbdfabce0,0x3d9dbdca,0x3d713de2,0x3dfdbc96,0x3d4fbdea,0x3da73dc2,0xbdf53d15,0xbbc93e00,0x3dd13d93,0xbddf3d7c,0xbc49bdff,0xbdf8bcf9,0xbdb93db1,0xbd21bdf3,
0x3db53d80,0x3c963dfd,0x3df33d21,0xbdd13d93,0xbda23dc6,0xbdacbdbe,0xbdf73d09,0x3d38bdef,0x3c49bdff,0x3df83cf9,0x3da7bdc2,0x3ce03dfa,0x3d713de2,0xbdf13d2c,0xbc7b3dfe,0xbdb9bdb1,
0xbdb53d80,0x3bc9be00,0xbdeabd4f,0x3df3bd21,0xbdf5bd15,0xbcf93df8,0x3dd13d93,0xbdfe3c7b,0x3de23d71,0x3d5bbde7,0xbdb1bdb9,0x3dff3c17,0xbdc6bda2,0xbd983dce,0x3d893dd8,0xbdf7bd09,
0x3db53d80,0xbcf93df8,0x3ddf3d7c,0xbe003b49,0xbc49bdff,0x3df1bd2c,0xbc17bdff,0x3d933dd1,0xbdc63da2,0xbdcebd98,0xbdca3d9d,0x3d38bdef,0x3df53d15,0xbbc93e00,0x3df33d21,0xbdfa3ce0,
0xbdb53d80,0x3d5bbde7,0xbdd1bd93,0x3df73d09,0x3de2bd71,0xbdcebd98,0xbdb93db1,0x3d66bde5,0xbd15bdf5,0xbdbe3dac,0x3d893dd8,0xbdcabd9d,0xbdff3c49,0x3d843ddc,0x3defbd38,0xbdc23da7,
0x3db53d80,0xbd983dce,0x3dc23da7,0xbdd8bd89,0x3dc63da2,0xbbc93e00,0x3dfe3c7b,0xbe003b49,0x3dff3c49,0x3d843ddc,0x3de5bd66,0xbdd13d93,0x3de2bd71,0x3de73d5b,0x3d7cbddf,0xbd383def,
0xbdb53d80,0x3dbebdac,0xbdb1bdb9,0x3da73dc2,0xbd153df5,0x3ddcbd84,0xbd89bdd8,0x3d7c3ddf,0xbd713de2,0x3df1bd2c,0xbd38bdef,0x3d213df3,0xbda23dc6,0x3dfdbc96,0xbcafbdfc,0x3c7b3dfe,
0x3db53d80,0xbddc3d84,0x3d9d3dca,0xbd4fbdea,0xbdff3c49,0xbde7bd5b,0xbd213df3,0x3d89bdd8,0xbda2bdc6,0xbc96bdfd,0xbdf73d09,0x3e00bb49,0x3d15bdf5,0x3dbebdac,0xbdc2bda7,0x3d933dd1,
0xbdb53d80,0x3df1bd2c,0xbd89bdd8,0x3c7b3dfe,0xbd71bde2,0x3c963dfd,0x3defbd38,0xbdffbc17,0x3df5bd15,0xbe00bbc9,0x3caf3dfc,0x3d09bdf7,0x3c493dff,0x3cf9bdf8,0xbe00bb49,0x3de53d66,
0x3db53d80,0xbdfd3c96,0x3d663de5,0x3cafbdfc,0x3da2bdc6,0x3dbebdac,0xbddfbd7c,0x3d4f3dea,0xbc493dff,0xbcf93df8,0x3dffbc17,0xbdd8bd89,0xbd71bde2,0xbd2cbdf1,0xbdca3d9d,0x3e00bb49,
0xbdb53d80,0x3e003bc9,0xbd38bdef,0xbd663de5,0x3df53d15,0xbdf8bcf9,0x3caf3dfc,0x3d9dbdca,0xbde2bd71,0x3de73d5b,0x3b49be00,0xbdc23da7,0x3dc63da2,0xbdcebd98,0xbce03dfa,0x3ddfbd7c,
0x3db53d80,0xbdf8bcf9,0x3d093df7,0x3db1bdb9,0x3c493dff,0x3d2c3df1,0x3da7bdc2,0xbdfcbcaf,0x3dc6bda2,0x3d98bdce,0xbdfebc7b,0x3d4f3dea,0xbdf5bd15,0xbe00bbc9,0x3d663de5,0x3d89bdd8,
0xbdb53d80,0x3de73d5b,0xbcafbdfc,0xbddf3d7c,0xbde23d71,0x3d98bdce,0xbe00bb49,0x3d213df3,0x3d153df5,0xbdacbdbe,0xbce03dfa,0x3dfebc7b,0x3dffbc49,0xbddc3d84,0x3dea3d4f,0x3c17bdff,
0x3db53d80,0xbdcebd98,0x3c173dff,0x3dfabce0,0xbdc6bda2,0xbe00bbc9,0x3d9d3dca,0x3db1bdb9,0xbdffbc49,0xbddc3d84,0x3df33d21,0x3cafbdfc,0xbde23d71,0xbd5b3de7,0x3df7bd09,0xbd4fbdea,
0xbdb53d80,0x3dac3dbe,0x3b49be00,0xbdffbc17,0x3d15bdf5,0x3d843ddc,0x3ce0bdfa,0xbdf7bd09,0x3d71bde2,0x3d2c3df1,0x3d4fbdea,0xbde5bd66,0x3da2bdc6,0x3c963dfd,0x3d93bdd1,0xbdcabd9d,
0x3db53d80,0xbd84bddc,0xbc7b3dfe,0x3def3d38,0x3dffbc49,0x3d5bbde7,0xbde53d66,0x3ce03dfa,0x3da23dc6,0x3dfdbc96,0xbddfbd7c,0xbdb13db9,0xbd153df5,0x3dac3dbe,0xbc17bdff,0xbdfcbcaf,
0xbdb53d80,0x3d2c3df1,0x3ce0bdfa,0xbdcabd9d,0x3d713de2,0xbdfd3c96,0x3dea3d4f,0x3dc2bda7,0xbdf53d15,0x3bc9be00,0xbd933dd1,0x3d7c3ddf,0xbc49bdff,0x3df83cf9,0xbdb1bdb9,0xbdf33d21,
0x3db53d80,0xbc96bdfd,0xbd213df3,0x3d933dd1,0xbda23dc6,0x3dac3dbe,0xbd09bdf7,0xbdefbd38,0x3c49bdff,0xbdf8bcf9,0x3dc23da7,0x3dfabce0,0x3d713de2,0x3df1bd2c,0xbdfebc7b,0xbdb13db9,
0xbdb53d80,0xbbc93e00,0x3d4fbdea,0xbd21bdf3,0xbdf5bd15,0x3cf9bdf8,0xbd933dd1,0x3c7b3dfe,0x3de23d71,0xbd5b3de7,0x3db9bdb1,0x3c17bdff,0xbdc6bda2,0x3d98bdce,0xbdd83d89,0xbd093df7,
0x3db53d80,0x3cf9bdf8,0xbd7c3ddf,0x3b493e00,0xbc49bdff,0xbdf13d2c,0x3dffbc17,0x3dd1bd93,0xbdc63da2,0x3dce3d98,0xbd9dbdca,0xbdefbd38,0x3df53d15,0x3bc9be00,0xbd213df3,0x3ce03dfa,
0xbdb53d80,0xbd5b3de7,0x3d93bdd1,0x3d09bdf7,0x3de2bd71,0x3dce3d98,0xbdb1bdb9,0xbde5bd66,0xbd15bdf5,0x3dbebdac,0xbdd83d89,0xbd9d3dca,0xbdff3c49,0xbd84bddc,0x3d383def,0x3da73dc2,
0x3db53d80,0x3d98bdce,0xbda73dc2,0xbd893dd8,0x3dc63da2,0x3bc9be00,0xbc7b3dfe,0x3b493e00,0x3dff3c49,0xbd84bddc,0x3d663de5,0x3d933dd1,0x3de2bd71,0xbde7bd5b,0x3ddf3d7c,0x3def3d38,
0xbcc83dfb,0xbc493dff,0xbbc93e00,0xbc963dfd,0xbd443ded,0xbd713de2,0xbd5b3de7,0xbd843ddc,0xbdb53db5,0xbdc63da2,0xbdbe3dac,0xbdce3d98,0xbded3d44,0xbdf53d15,0xbdf13d2c,0xbdf83cf9,
0xbd8e3dd5,0xbd153df5,0xbc963dfd,0xbd5b3de7,0xbded3d44,0xbdff3c49,0xbdf83cf9,0xbe00bbc9,0xbdb5bdb5,0xbd71bde2,0xbd98bdce,0xbd2cbdf1,0x3d44bded,0x3da2bdc6,0x3d84bddc,0x3dbebdac,
0xbdd53d8e,0xbd713de2,0xbcf93df8,0xbdac3dbe,0xbdedbd44,0xbda2bdc6,0xbdcebd98,0xbd5bbde7,0x3db5bdb5,0x3df5bd15,0x3ddcbd84,0x3e00bbc9,0x3d443ded,0xbc493dff,0x3c963dfd,0xbd2c3df1,
0xbdfb3cc8,0xbda23dc6,0xbd2c3df1,0xbddc3d84,0xbd44bded,0x3d15bdf5,0xbbc9be00,0x3d98bdce,0x3db53db5,0x3c493dff,0x3d5b3de7,0xbcf93df8,0xbdedbd44,0xbd71bde2,0xbdbebdac,0xbc96bdfd,
0xbdfbbcc8,0xbdc63da2,0xbd5b3de7,0xbdf83cf9,0x3d44bded,0x3df5bd15,0x3dbebdac,0x3dfd3c96,0xbdb53db5,0xbdffbc49,0xbdf13d2c,0xbddcbd84,0x3dedbd44,0x3de23d71,0x3e003bc9,0x3d983dce,
0xbdd5bd8e,0xbde23d71,0xbd843ddc,0xbe00bbc9,0x3dedbd44,0x3dc63da2,0x3dfd3c96,0x3d2c3df1,0xbdb5bdb5,0x3d15bdf5,0xbcf9bdf8,0x3dbebdac,0xbd443ded,0xbdff3c49,0xbdce3d98,0xbde7bd5b,
0xbd8ebdd5,0xbdf53d15,0xbd983dce,0xbdf1bd2c,0x3ded3d44,0xbc493dff,0x3d843ddc,0xbdac3dbe,0x3db5bdb5,0x3de23d71,0x3dfdbc96,0x3d5b3de7,0xbd44bded,0x3dc6bda2,0x3cf9bdf8,0x3e00bbc9,
0xbcc8bdfb,0xbdff3c49,0xbdac3dbe,0xbdcebd98,0x3d443ded,0xbde23d71,0xbd2c3df1,0xbdf8bcf9,0x3db53db5,0xbda23dc6,0x3bc93e00,0xbdfd3c96,0x3ded3d44,0xbd153df5,0x3d5b3de7,0xbddc3d84,
0x3cc8bdfb,0xbdffbc49,0xbdbe3dac,0xbd98bdce,0xbd443ded,0xbde2bd71,0xbdf13d2c,0xbcf9bdf8,0xbdb53db5,0xbda2bdc6,0xbe00bbc9,0x3c96bdfd,0xbded3d44,0xbd15bdf5,0xbde7bd5b,0x3d84bddc,
0x3d8ebdd5,0xbdf5bd15,0xbdce3d98,0xbd2cbdf1,0xbded3d44,0xbc49bdff,0xbddcbd84,0x3dbebdac,0xbdb5bdb5,0x3de2bd71,0x3c96bdfd,0x3de73d5b,0x3d44bded,0x3dc63da2,0x3df8bcf9,0xbbc93e00,
0x3dd5bd8e,0xbde2bd71,0xbddc3d84,0xbbc9be00,0xbdedbd44,0x3dc6bda2,0xbc96bdfd,0x3df13d2c,0x3db5bdb5,0x3d153df5,0x3df83cf9,0xbdac3dbe,0x3d443ded,0xbdffbc49,0xbd983dce,0xbd5bbde7,
0x3dfbbcc8,0xbdc6bda2,0xbde73d5b,0x3cf9bdf8,0xbd44bded,0x3df53d15,0x3dacbdbe,0x3c963dfd,0x3db53db5,0xbdff3c49,0xbd2c3df1,0xbd84bddc,0xbdedbd44,0x3de2bd71,0xbbc9be00,0x3dce3d98,
0x3dfb3cc8,0xbda2bdc6,0xbdf13d2c,0x3d84bddc,0x3d44bded,0x3d153df5,0x3e003bc9,0xbdce3d98,0xbdb53db5,0x3c49bdff,0xbde7bd5b,0x3df8bcf9,0x3dedbd44,0xbd713de2,0x3dac3dbe,0xbdfdbc96,
0x3dd53d8e,0xbd71bde2,0xbdf83cf9,0x3dbebdac,0x3dedbd44,0xbda23dc6,0x3d983dce,0xbde7bd5b,0xbdb5bdb5,0x3df53d15,0x3d84bddc,0xbbc93e00,0xbd443ded,0xbc49bdff,0xbdfdbc96,0x3df1bd2c,
0x3d8e3dd5,0xbd15bdf5,0xbdfd3c96,0x3de7bd5b,0x3ded3d44,0xbdffbc49,0xbcf93df8,0xbbc9be00,0x3db5bdb5,0xbd713de2,0x3dce3d98,0xbdf1bd2c,0xbd44bded,0x3da23dc6,0x3ddcbd84,0xbdac3dbe,
0x3cc83dfb,0xbc49bdff,0xbe003bc9,0x3dfdbc96,0x3d443ded,0xbd71bde2,0xbde73d5b,0x3ddcbd84,0x3db53db5,0xbdc6bda2,0xbdac3dbe,0x3d98bdce,0x3ded3d44,0xbdf5bd15,0xbd2c3df1,0x3cf9bdf8,
0xbcc83dfb,0x3c49bdff,0xbe00bbc9,0x3dfd3c96,0xbd443ded,0x3d71bde2,0xbde7bd5b,0x3ddc3d84,0xbdb53db5,0x3dc6bda2,0xbdacbdbe,0x3d983dce,0xbded3d44,0x3df5bd15,0xbd2cbdf1,0x3cf93df8,
0xbd8e3dd5,0x3d15bdf5,0xbdfdbc96,0x3de73d5b,0xbded3d44,0x3dffbc49,0xbcf9bdf8,0xbbc93e00,0xbdb5bdb5,0x3d713de2,0x3dcebd98,0xbdf13d2c,0x3d44bded,0xbda23dc6,0x3ddc3d84,0xbdacbdbe,
0xbdd53d8e,0x3d71bde2,0xbdf8bcf9,0x3dbe3dac,0xbdedbd44,0x3da23dc6,0x3d98bdce,0xbde73d5b,0x3db5bdb5,0xbdf53d15,0x3d843ddc,0xbbc9be00,0x3d443ded,0x3c49bdff,0xbdfd3c96,0x3df13d2c,
0xbdfb3cc8,0x3da2bdc6,0xbdf1bd2c,0x3d843ddc,0xbd44bded,0xbd153df5,0x3e00bbc9,0xbdcebd98,0x3db53db5,0xbc49bdff,0xbde73d5b,0x3df83cf9,0xbdedbd44,0x3d713de2,0x3dacbdbe,0xbdfd3c96,
0xbdfbbcc8,0x3dc6bda2,0xbde7bd5b,0x3cf93df8,0x3d44bded,0xbdf53d15,0x3dac3dbe,0x3c96bdfd,0xbdb53db5,0x3dff3c49,0xbd2cbdf1,0xbd843ddc,0x3dedbd44,0xbde2bd71,0xbbc93e00,0x3dcebd98,
0xbdd5bd8e,0x3de2bd71,0xbddcbd84,0xbbc93e00,0x3dedbd44,0xbdc6bda2,0xbc963dfd,0x3df1bd2c,0xbdb5bdb5,0xbd153df5,0x3df8bcf9,0xbdacbdbe,0xbd443ded,0x3dffbc49,0xbd98bdce,0xbd5b3de7,
0xbd8ebdd5,0x3df5bd15,0xbdcebd98,0xbd2c3df1,0x3ded3d44,0x3c49bdff,0xbddc3d84,0x3dbe3dac,0x3db5bdb5,0xbde2bd71,0x3c963dfd,0x3de7bd5b,0xbd44bded,0xbdc63da2,0x3df83cf9,0xbbc9be00,
0xbcc8bdfb,0x3dffbc49,0xbdbebdac,0xbd983dce,0x3d443ded,0x3de2bd71,0xbdf1bd2c,0xbcf93df8,0x3db53db5,0x3da2bdc6,0xbe003bc9,0x3c963dfd,0x3ded3d44,0x3d15bdf5,0xbde73d5b,0x3d843ddc,
0x3cc8bdfb,0x3dff3c49,0xbdacbdbe,0xbdce3d98,0xbd443ded,0x3de23d71,0xbd2cbdf1,0xbdf83cf9,0xbdb53db5,0x3da23dc6,0x3bc9be00,0xbdfdbc96,0xbded3d44,0x3d153df5,0x3d5bbde7,0xbddcbd84,
0x3d8ebdd5,0x3df53d15,0xbd98bdce,0xbdf13d2c,0xbded3d44,0x3c493dff,0x3d84bddc,0xbdacbdbe,0xbdb5bdb5,0xbde23d71,0x3dfd3c96,0x3d5bbde7,0x3d44bded,0xbdc6bda2,0x3cf93df8,0x3e003bc9,
0x3dd5bd8e,0x3de23d71,0xbd84bddc,0xbe003bc9,0xbdedbd44,0xbdc63da2,0x3dfdbc96,0x3d2cbdf1,0x3db5bdb5,0xbd15bdf5,0xbcf93df8,0x3dbe3dac,0x3d443ded,0x3dff3c49,0xbdcebd98,0xbde73d5b,
0x3dfbbcc8,0x3dc63da2,0xbd5bbde7,0xbdf8bcf9,0xbd44bded,0xbdf5bd15,0x3dbe3dac,0x3dfdbc96,0x3db53db5,0x3dffbc49,0xbdf1bd2c,0xbddc3d84,0xbdedbd44,0xbde23d71,0x3e00bbc9,0x3d98bdce,
0x3dfb3cc8,0x3da23dc6,0xbd2cbdf1,0xbddcbd84,0x3d44bded,0xbd15bdf5,0xbbc93e00,0x3d983dce,0xbdb53db5,0xbc493dff,0x3d5bbde7,0xbcf9bdf8,0x3dedbd44,0x3d71bde2,0xbdbe3dac,0xbc963dfd,
0x3dd53d8e,0x3d713de2,0xbcf9bdf8,0xbdacbdbe,0x3dedbd44,0x3da2bdc6,0xbdce3d98,0xbd5b3de7,0xbdb5bdb5,0xbdf5bd15,0x3ddc3d84,0x3e003bc9,0xbd443ded,0x3c493dff,0x3c96bdfd,0xbd2cbdf1,
0x3d8e3dd5,0x3d153df5,0xbc96bdfd,0xbd5bbde7,0x3ded3d44,0x3dff3c49,0xbdf8bcf9,0xbe003bc9,0x3db5bdb5,0x3d71bde2,0xbd983dce,0xbd2c3df1,0xbd44bded,0xbda2bdc6,0x3d843ddc,0x3dbe3dac,
0x3cc83dfb,0x3c493dff,0xbbc9be00,0xbc96bdfd,0x3d443ded,0x3d713de2,0xbd5bbde7,0xbd84bddc,0x3db53db5,0x3dc63da2,0xbdbebdac,0xbdcebd98,0x3ded3d44,0x3df53d15,0xbdf1bd2c,0xbdf8bcf9,
0xbd803d80,0xbdffbc49,0xbe00bbc9,0xbdfdbc96,0xbd8e3dd5,0xbde2bd71,0xbde7bd5b,0xbddcbd84,0xbdd53d8e,0xbda2bdc6,0xbdacbdbe,0xbd98bdce,0xbdfb3cc8,0xbd15bdf5,0xbd2cbdf1,0xbcf9bdf8,
0x3d803d80,0x3df53d15,0x3dfd3c96,0x3de73d5b,0xbdfbbcc8,0x3c493dff,0x3cf93df8,0xbbc93e00,0xbcc8bdfb,0xbde23d71,0xbdce3d98,0xbdf13d2c,0x3dd5bd8e,0xbdc6bda2,0xbddcbd84,0xbdacbdbe,
0xbd803d80,0xbde2bd71,0xbdf8bcf9,0xbdbebdac,0xbcc8bdfb,0x3dc6bda2,0x3d98bdce,0x3de7bd5b,0x3dfb3cc8,0x3d153df5,0x3d843ddc,0x3bc93e00,0xbd8e3dd5,0xbdffbc49,0xbdfd3c96,0xbdf1bd2c,
0x3d803d80,0x3dc63da2,0x3df13d2c,0x3d843ddc,0x3dd5bd8e,0xbdf5bd15,0xbe003bc9,0xbdcebd98,0xbd8e3dd5,0x3dffbc49,0x3de7bd5b,0x3df83cf9,0x3cc8bdfb,0xbde23d71,0xbdac3dbe,0xbdfd3c96,
0xbd803d80,0xbda2bdc6,0xbde7bd5b,0xbcf9bdf8,0x3dd53d8e,0x3d153df5,0x3dac3dbe,0xbc963dfd,0xbd8ebdd5,0x3c49bdff,0xbd2cbdf1,0x3d84bddc,0x3cc83dfb,0xbd713de2,0xbbc93e00,0xbdce3d98,
0x3d803d80,0x3d713de2,0x3ddc3d84,0xbbc93e00,0xbcc83dfb,0x3da2bdc6,0x3c96bdfd,0x3df1bd2c,0x3dfbbcc8,0xbdf5bd15,0xbdf83cf9,0xbdacbdbe,0xbd8ebdd5,0x3c493dff,0x3d983dce,0xbd5b3de7,
0xbd803d80,0xbd15bdf5,0xbdcebd98,0x3d2cbdf1,0xbdfb3cc8,0xbdffbc49,0xbddc3d84,0xbdbebdac,0xbcc83dfb,0xbd713de2,0x3c963dfd,0xbde73d5b,0x3dd53d8e,0x3da23dc6,0x3df83cf9,0x3bc93e00,
0x3d803d80,0x3c493dff,0x3dbe3dac,0xbd983dce,0xbd8ebdd5,0x3d713de2,0x3df13d2c,0xbcf93df8,0xbdd5bd8e,0x3dc63da2,0x3e00bbc9,0x3c963dfd,0xbdfbbcc8,0x3df53d15,0x3de7bd5b,0x3d843ddc,
0xbd803d80,0x3c49bdff,0xbdacbdbe,0x3dcebd98,0x3d8ebdd5,0x3d71bde2,0xbd2cbdf1,0x3df8bcf9,0x3dd5bd8e,0x3dc6bda2,0x3bc9be00,0x3dfd3c96,0x3dfbbcc8,0x3df5bd15,0x3d5bbde7,0x3ddc3d84,
0x3d803d80,0xbd153df5,0x3d983dce,0xbdf13d2c,0x3dfb3cc8,0xbdff3c49,0xbd843ddc,0xbdacbdbe,0x3cc83dfb,0xbd71bde2,0xbdfdbc96,0x3d5bbde7,0xbdd53d8e,0x3da2bdc6,0xbcf9bdf8,0x3e003bc9,
0xbd803d80,0x3d71bde2,0xbd84bddc,0x3e00bbc9,0x3cc83dfb,0x3da23dc6,0x3dfdbc96,0xbd2c3df1,0xbdfbbcc8,0xbdf53d15,0xbcf93df8,0xbdbebdac,0x3d8ebdd5,0x3c49bdff,0xbdcebd98,0x3de7bd5b,
0x3d803d80,0xbda23dc6,0x3d5b3de7,0xbdf8bcf9,0xbdd53d8e,0x3d15bdf5,0xbdbebdac,0x3dfdbc96,0x3d8ebdd5,0x3c493dff,0x3df13d2c,0xbddc3d84,0xbcc83dfb,0xbd71bde2,0xbe003bc9,0x3d98bdce,
0xbd803d80,0x3dc6bda2,0xbd2cbdf1,0x3ddc3d84,0xbdd5bd8e,0xbdf53d15,0xbbc93e00,0xbd98bdce,0x3d8e3dd5,0x3dff3c49,0x3d5bbde7,0x3cf93df8,0xbcc8bdfb,0xbde2bd71,0xbdbe3dac,0x3c96bdfd,
0x3d803d80,0xbde23d71,0x3cf93df8,0xbdacbdbe,0x3cc8bdfb,0x3dc63da2,0x3dcebd98,0xbd5b3de7,0xbdfb3cc8,0x3d15bdf5,0xbddcbd84,0x3e003bc9,0x3d8e3dd5,0xbdff3c49,0xbc963dfd,0xbd2cbdf1,
0xbd803d80,0x3df5bd15,0xbc96bdfd,0x3d5b3de7,0x3dfbbcc8,0x3c49bdff,0xbdf8bcf9,0x3e00bbc9,0x3cc8bdfb,0xbde2bd71,0xbd983dce,0x3d2cbdf1,0xbdd5bd8e,0xbdc63da2,0x3d843ddc,0xbdbebdac,
0x3d803d80,0xbdff3c49,0x3bc93e00,0xbc96bdfd,0x3d8e3dd5,0xbde23d71,0x3d5b3de7,0xbd84bddc,0x3dd53d8e,0xbda23dc6,0x3dbe3dac,0xbdcebd98,0x3dfb3cc8,0xbd153df5,0x3df13d2c,0xbdf8bcf9,
0xbd803d80,0x3dff3c49,0x3bc9be00,0xbc963dfd,0xbd8e3dd5,0x3de23d71,0x3d5bbde7,0xbd843ddc,0xbdd53d8e,0x3da23dc6,0x3dbebdac,0xbdce3d98,0xbdfb3cc8,0x3d153df5,0x3df1bd2c,0xbdf83cf9,
0x3d803d80,0xbdf5bd15,0xbc963dfd,0x3d5bbde7,0xbdfbbcc8,0xbc49bdff,0xbdf83cf9,0x3e003bc9,0xbcc8bdfb,0x3de2bd71,0xbd98bdce,0x3d2c3df1,0x3dd5bd8e,0x3dc63da2,0x3d84bddc,0xbdbe3dac,
0xbd803d80,0x3de23d71,0x3cf9bdf8,0xbdac3dbe,0xbcc8bdfb,0xbdc63da2,0x3dce3d98,0xbd5bbde7,0x3dfb3cc8,0xbd15bdf5,0xbddc3d84,0x3e00bbc9,0xbd8e3dd5,0x3dff3c49,0xbc96bdfd,0xbd2c3df1,
0x3d803d80,0xbdc6bda2,0xbd2c3df1,0x3ddcbd84,0x3dd5bd8e,0x3df53d15,0xbbc9be00,0xbd983dce,0xbd8e3dd5,0xbdff3c49,0x3d5b3de7,0x3cf9bdf8,0x3cc8bdfb,0x3de2bd71,0xbdbebdac,0x3c963dfd,
0xbd803d80,0x3da23dc6,0x3d5bbde7,0xbdf83cf9,0x3dd53d8e,0xbd15bdf5,0xbdbe3dac,0x3dfd3c96,0xbd8ebdd5,0xbc493dff,0x3df1bd2c,0xbddcbd84,0x3cc83dfb,0x3d71bde2,0xbe00bbc9,0x3d983dce,
0x3d803d80,0xbd71bde2,0xbd843ddc,0x3e003bc9,0xbcc83dfb,0xbda23dc6,0x3dfd3c96,0xbd2cbdf1,0x3dfbbcc8,0x3df53d15,0xbcf9bdf8,0xbdbe3dac,0xbd8ebdd5,0xbc49bdff,0xbdce3d98,0x3de73d5b,
0xbd803d80,0x3d153df5,0x3d98bdce,0xbdf1bd2c,0xbdfb3cc8,0x3dff3c49,0xbd84bddc,0xbdac3dbe,0xbcc83dfb,0x3d71bde2,0xbdfd3c96,0x3d5b3de7,0x3dd53d8e,0xbda2bdc6,0xbcf93df8,0x3e00bbc9,
0x3d803d80,0xbc49bdff,0xbdac3dbe,0x3dce3d98,0xbd8ebdd5,0xbd71bde2,0xbd2c3df1,0x3df83cf9,0xbdd5bd8e,0xbdc6bda2,0x3bc93e00,0x3dfdbc96,0xbdfbbcc8,0xbdf5bd15,0x3d5b3de7,0x3ddcbd84,
0xbd803d80,0xbc493dff,0x3dbebdac,0xbd98bdce,0x3d8ebdd5,0xbd713de2,0x3df1bd2c,0xbcf9bdf8,0x3dd5bd8e,0xbdc63da2,0x3e003bc9,0x3c96bdfd,0x3dfbbcc8,0xbdf53d15,0x3de73d5b,0x3d84bddc,
0x3d803d80,0x3d15bdf5,0xbdce3d98,0x3d2c3df1,0x3dfb3cc8,0x3dffbc49,0xbddcbd84,0xbdbe3dac,0x3cc83dfb,0x3d713de2,0x3c96bdfd,0xbde7bd5b,0xbdd53d8e,0xbda23dc6,0x3df8bcf9,0x3bc9be00,
0xbd803d80,0xbd713de2,0x3ddcbd84,0xbbc9be00,0x3cc83dfb,0xbda2bdc6,0x3c963dfd,0x3df13d2c,0xbdfbbcc8,0x3df5bd15,0xbdf8bcf9,0xbdac3dbe,0x3d8ebdd5,0xbc493dff,0x3d98bdce,0xbd5bbde7,
0x3d803d80,0x3da2bdc6,0xbde73d5b,0xbcf93df8,0xbdd53d8e,0xbd153df5,0x3dacbdbe,0xbc96bdfd,0x3d8ebdd5,0xbc49bdff,0xbd2c3df1,0x3d843ddc,0xbcc83dfb,0x3d713de2,0xbbc9be00,0xbdcebd98,
0xbd803d80,0xbdc63da2,0x3df1bd2c,0x3d84bddc,0xbdd5bd8e,0x3df5bd15,0xbe00bbc9,0xbdce3d98,0x3d8e3dd5,0xbdffbc49,0x3de73d5b,0x3df8bcf9,0xbcc8bdfb,0x3de23d71,0xbdacbdbe,0xbdfdbc96,
0x3d803d80,0x3de2bd71,0xbdf83cf9,0xbdbe3dac,0x3cc8bdfb,0xbdc6bda2,0x3d983dce,0x3de73d5b,0xbdfb3cc8,0xbd153df5,0x3d84bddc,0x3bc9be00,0x3d8e3dd5,0x3dffbc49,0xbdfdbc96,0xbdf13d2c,
0xbd803d80,0xbdf53d15,0x3dfdbc96,0x3de7bd5b,0x3dfbbcc8,0xbc493dff,0x3cf9bdf8,0xbbc9be00,0x3cc8bdfb,0x3de23d71,0xbdcebd98,0xbdf1bd2c,0xbdd5bd8e,0x3dc6bda2,0xbddc3d84,0xbdac3dbe,
0x3d803d80,0x3dffbc49,0xbe003bc9,0xbdfd3c96,0x3d8e3dd5,0x3de2bd71,0xbde73d5b,0xbddc3d84,0x3dd53d8e,0x3da2bdc6,0xbdac3dbe,0xbd983dce,0x3dfb3cc8,0x3d15bdf5,0xbd2c3df1,0xbcf93df8,
0xbd153df5,0xbc963dfd,0xbc173dff,0xbce03dfa,0xbd8e3dd5,0xbdac3dbe,0xbd9d3dca,0xbdb93db1,0xbded3d44,0xbdf83cf9,0xbdf33d21,0xbdfc3caf,0xbdfbbcc8,0xbdf1bd2c,0xbdf7bd09,0xbdeabd4f,
0xbda23dc6,0xbd2c3df1,0xbcaf3dfc,0xbd7c3ddf,0xbdfb3cc8,0xbdfdbc96,0xbe003b49,0xbdf3bd21,0xbd44bded,0xbbc9be00,0xbce0bdfa,0x3c7bbdfe,0x3dd5bd8e,0x3df8bcf9,0x3deabd4f,0x3dffbc17,
0xbde23d71,0xbd843ddc,0xbd093df7,0xbdb93db1,0xbdd5bd8e,0xbd5bbde7,0xbda7bdc2,0xbcafbdfc,0x3dedbd44,0x3dfd3c96,0x3dfebc7b,0x3dea3d4f,0xbcc83dfb,0xbdac3dbe,0xbd663de5,0xbdd83d89,
0xbdff3c49,0xbdac3dbe,0xbd383def,0xbde53d66,0xbcc8bdfb,0x3d84bddc,0x3cafbdfc,0x3dcabd9d,0x3d443ded,0xbd2c3df1,0x3b493e00,0xbda73dc2,0xbd8ebdd5,0x3c96bdfd,0xbce0bdfa,0x3d7cbddf,
0xbdf5bd15,0xbdce3d98,0xbd663de5,0xbdfc3caf,0x3d8ebdd5,0x3e00bbc9,0x3ddfbd7c,0x3dea3d4f,0xbded3d44,0xbddcbd84,0xbdffbc17,0xbd89bdd8,0x3dfb3cc8,0x3d5b3de7,0x3dca3d9d,0xbb493e00,
0xbdc6bda2,0xbde73d5b,0xbd893dd8,0xbdfebc7b,0x3dfbbcc8,0x3d983dce,0x3def3d38,0x3c173dff,0xbd44bded,0x3dacbdbe,0x3cafbdfc,0x3df7bd09,0xbdd53d8e,0xbddcbd84,0xbe003b49,0xbd66bde5,
0xbd71bde2,0xbdf83cf9,0xbd9d3dca,0xbdeabd4f,0x3dd53d8e,0xbd2c3df1,0x3d213df3,0xbdd83d89,0x3dedbd44,0x3d983dce,0x3df73d09,0xbb493e00,0x3cc8bdfb,0x3e00bbc9,0x3dc2bda7,0x3dd13d93,
0xbc49bdff,0xbe003bc9,0xbdb13db9,0xbdc2bda7,0x3cc83dfb,0xbdf83cf9,0xbd893dd8,0xbddfbd7c,0x3d443ded,0xbde73d5b,0xbd383def,0xbdf3bd21,0x3d8e3dd5,0xbdce3d98,0xbcaf3dfc,0xbdfebc7b,
0x3d15bdf5,0xbdfdbc96,0xbdc23da7,0xbd89bdd8,0xbd8e3dd5,0xbdbebdac,0xbdfe3c7b,0x3b49be00,0xbded3d44,0xbcf9bdf8,0xbde5bd66,0x3d93bdd1,0xbdfbbcc8,0x3d2cbdf1,0xbd7cbddf,0x3defbd38,
0x3da2bdc6,0xbdf1bd2c,0xbdd13d93,0xbd09bdf7,0xbdfb3cc8,0x3c96bdfd,0xbdb9bdb1,0x3de5bd66,0xbd44bded,0x3e00bbc9,0x3d89bdd8,0x3d9d3dca,0x3dd5bd8e,0x3cf93df8,0x3def3d38,0xbda73dc2,
0x3de2bd71,0xbddcbd84,0xbddf3d7c,0x3b49be00,0xbdd5bd8e,0x3de7bd5b,0x3c17bdff,0x3dd13d93,0x3dedbd44,0xbc963dfd,0x3dca3d9d,0xbdef3d38,0xbcc83dfb,0xbdbebdac,0xbdf33d21,0x3ce0bdfa,
0x3dffbc49,0xbdbebdac,0xbdea3d4f,0x3d21bdf3,0xbcc8bdfb,0x3ddc3d84,0x3dd1bd93,0xbc7b3dfe,0x3d443ded,0xbdf1bd2c,0xbdb13db9,0xbc17bdff,0xbd8ebdd5,0x3dfd3c96,0x3d89bdd8,0x3d093df7,
0x3df53d15,0xbd98bdce,0xbdf33d21,0x3d93bdd1,0x3d8ebdd5,0x3bc93e00,0x3df73d09,0xbdef3d38,0xbded3d44,0x3d84bddc,0xbda7bdc2,0x3dfa3ce0,0x3dfb3cc8,0xbde73d5b,0x3c7b3dfe,0xbdb1bdb9,
0x3dc63da2,0xbd5bbde7,0xbdfa3ce0,0x3dcabd9d,0x3dfbbcc8,0xbdce3d98,0x3d4f3dea,0xbdc2bda7,0xbd44bded,0x3dbe3dac,0x3dd1bd93,0xbd7c3ddf,0xbdd53d8e,0x3d84bddc,0xbdb9bdb1,0x3df33d21,
0x3d713de2,0xbcf9bdf8,0xbdfe3c7b,0x3defbd38,0x3dd53d8e,0xbdf1bd2c,0xbd663de5,0x3ce0bdfa,0x3dedbd44,0xbdce3d98,0x3d7c3ddf,0xbdb1bdb9,0x3cc8bdfb,0x3bc93e00,0x3dff3c17,0xbdfc3caf,
0x3c493dff,0xbbc9be00,0xbe003b49,0x3dffbc17,0x3cc83dfb,0xbcf9bdf8,0xbdfa3ce0,0x3df7bd09,0x3d443ded,0xbd5bbde7,0xbdea3d4f,0x3de5bd66,0x3d8e3dd5,0xbd98bdce,0xbdd13d93,0x3dcabd9d,
0xbd153df5,0x3c96bdfd,0xbdffbc17,0x3dfa3ce0,0xbd8e3dd5,0x3dacbdbe,0xbdcabd9d,0x3db13db9,0xbded3d44,0x3df8bcf9,0xbd21bdf3,0x3caf3dfc,0xbdfbbcc8,0x3df13d2c,0x3d09bdf7,0xbd4f3dea,
0xbda23dc6,0x3d2cbdf1,0xbdfcbcaf,0x3ddf3d7c,0xbdfb3cc8,0x3dfd3c96,0xbb49be00,0xbd213df3,0xbd44bded,0x3bc93e00,0x3dfabce0,0xbdfebc7b,0x3dd5bd8e,0xbdf83cf9,0x3d4f3dea,0xbc17bdff,
0xbde23d71,0x3d84bddc,0xbdf7bd09,0x3db13db9,0xbdd5bd8e,0x3d5b3de7,0x3dc2bda7,0xbdfc3caf,0x3dedbd44,0xbdfdbc96,0x3c7b3dfe,0x3d4fbdea,0xbcc83dfb,0x3dacbdbe,0xbde5bd66,0x3d893dd8,
0xbdff3c49,0x3dacbdbe,0xbdefbd38,0x3d663de5,0xbcc8bdfb,0xbd843ddc,0x3dfc3caf,0xbd9dbdca,0x3d443ded,0x3d2cbdf1,0xbe003b49,0x3dc23da7,0xbd8ebdd5,0xbc963dfd,0x3dfabce0,0xbddfbd7c,
0xbdf5bd15,0x3dcebd98,0xbde5bd66,0x3caf3dfc,0x3d8ebdd5,0xbe003bc9,0x3d7c3ddf,0x3d4fbdea,0xbded3d44,0x3ddc3d84,0x3c17bdff,0xbdd83d89,0x3dfb3cc8,0xbd5bbde7,0xbd9d3dca,0x3e003b49,
0xbdc6bda2,0x3de7bd5b,0xbdd8bd89,0xbc7b3dfe,0x3dfbbcc8,0xbd98bdce,0xbd383def,0x3dffbc17,0xbd44bded,0xbdac3dbe,0x3dfc3caf,0xbd09bdf7,0xbdd53d8e,0x3ddc3d84,0xbb49be00,0xbde53d66,
0xbd71bde2,0x3df8bcf9,0xbdcabd9d,0xbd4f3dea,0x3dd53d8e,0x3d2cbdf1,0xbdf33d21,0x3d893dd8,0x3dedbd44,0xbd98bdce,0xbd093df7,0x3e003b49,0x3cc8bdfb,0xbe003bc9,0x3da73dc2,0x3d93bdd1,
0xbc49bdff,0x3e00bbc9,0xbdb9bdb1,0xbda73dc2,0x3cc83dfb,0x3df8bcf9,0xbdd8bd89,0xbd7c3ddf,0x3d443ded,0x3de7bd5b,0xbdefbd38,0xbd213df3,0x3d8e3dd5,0x3dcebd98,0xbdfcbcaf,0xbc7b3dfe,
0x3d15bdf5,0x3dfd3c96,0xbda7bdc2,0xbdd83d89,0xbd8e3dd5,0x3dbe3dac,0xbc7bbdfe,0xbe00bb49,0xbded3d44,0x3cf93df8,0x3d66bde5,0xbdd1bd93,0xbdfbbcc8,0xbd2c3df1,0x3ddfbd7c,0xbd38bdef,
0x3da2bdc6,0x3df13d2c,0xbd93bdd1,0xbdf73d09,0xbdfb3cc8,0xbc963dfd,0x3db1bdb9,0xbd66bde5,0xbd44bded,0xbe003bc9,0x3dd83d89,0x3dcabd9d,0x3dd5bd8e,0xbcf9bdf8,0xbd383def,0x3dc23da7,
0x3de2bd71,0x3ddc3d84,0xbd7cbddf,0xbe00bb49,0xbdd5bd8e,0xbde73d5b,0x3dff3c17,0x3d93bdd1,0x3dedbd44,0x3c96bdfd,0xbd9d3dca,0x3d383def,0xbcc83dfb,0x3dbe3dac,0xbd21bdf3,0xbdfabce0,
0x3dffbc49,0x3dbe3dac,0xbd4fbdea,0xbdf3bd21,0xbcc8bdfb,0xbddcbd84,0x3d933dd1,0x3dfe3c7b,0x3d443ded,0x3df13d2c,0xbdb9bdb1,0xbdff3c17,0xbd8ebdd5,0xbdfdbc96,0x3dd83d89,0x3df7bd09,
0x3df53d15,0x3d983dce,0xbd21bdf3,0xbdd1bd93,0x3d8ebdd5,0xbbc9be00,0xbd093df7,0x3d383def,0xbded3d44,0xbd843ddc,0x3dc2bda7,0x3ce0bdfa,0x3dfb3cc8,0x3de7bd5b,0xbdfe3c7b,0xbdb93db1,
0x3dc63da2,0x3d5b3de7,0xbce0bdfa,0xbd9dbdca,0x3dfbbcc8,0x3dcebd98,0xbdea3d4f,0xbda73dc2,0xbd44bded,0xbdbebdac,0x3d933dd1,0x3ddf3d7c,0xbdd53d8e,0xbd843ddc,0x3db1bdb9,0x3d21bdf3,
0x3d713de2,0x3cf93df8,0xbc7bbdfe,0xbd38bdef,0x3dd53d8e,0x3df13d2c,0xbde5bd66,0xbdfabce0,0x3dedbd44,0x3dcebd98,0xbddf3d7c,0xbdb93db1,0x3cc8bdfb,0xbbc9be00,0xbc173dff,0x3caf3dfc,
0x3c493dff,0x3bc93e00,0xbb49be00,0xbc17bdff,0x3cc83dfb,0x3cf93df8,0xbce0bdfa,0xbd09bdf7,0x3d443ded,0x3d5b3de7,0xbd4fbdea,0xbd66bde5,0x3d8e3dd5,0x3d983dce,0xbd93bdd1,0xbd9dbdca,
0xbdb53d80,0xbd98bdce,0xbda7bdc2,0xbd89bdd8,0xbdc63da2,0xbbc9be00,0xbc7bbdfe,0x3b49be00,0xbdff3c49,0x3d84bddc,0x3d66bde5,0x3d93bdd1,0xbde2bd71,0x3de7bd5b,0x3ddfbd7c,0x3defbd38,
0x3db53d80,0x3d5b3de7,0x3d933dd1,0x3d093df7,0xbde2bd71,0xbdce3d98,0xbdb13db9,0xbde53d66,0x3d15bdf5,0xbdbebdac,0xbdd8bd89,0xbd9dbdca,0x3dff3c49,0x3d84bddc,0x3d38bdef,0x3da7bdc2,
0xbdb53d80,0xbcf9bdf8,0xbd7cbddf,0x3b49be00,0x3c49bdff,0x3df13d2c,0x3dff3c17,0x3dd13d93,0x3dc63da2,0xbdce3d98,0xbd9d3dca,0xbdef3d38,0xbdf53d15,0xbbc9be00,0xbd21bdf3,0x3ce0bdfa,
0x3db53d80,0x3bc93e00,0x3d4f3dea,0xbd213df3,0x3df5bd15,0xbcf9bdf8,0xbd93bdd1,0x3c7bbdfe,0xbde23d71,0x3d5b3de7,0x3db93db1,0x3c173dff,0x3dc6bda2,0xbd98bdce,0xbdd8bd89,0xbd09bdf7,
0xbdb53d80,0x3c96bdfd,0xbd21bdf3,0x3d93bdd1,0x3da23dc6,0xbdac3dbe,0xbd093df7,0xbdef3d38,0xbc49bdff,0x3df8bcf9,0x3dc2bda7,0x3dfa3ce0,0xbd713de2,0xbdf1bd2c,0xbdfe3c7b,0xbdb1bdb9,
0x3db53d80,0xbd2c3df1,0x3ce03dfa,0xbdca3d9d,0xbd713de2,0x3dfd3c96,0x3deabd4f,0x3dc23da7,0x3df53d15,0xbbc9be00,0xbd93bdd1,0x3d7cbddf,0x3c49bdff,0xbdf83cf9,0xbdb13db9,0xbdf3bd21,
0xbdb53d80,0x3d84bddc,0xbc7bbdfe,0x3defbd38,0xbdffbc49,0xbd5bbde7,0xbde5bd66,0x3ce0bdfa,0xbda23dc6,0xbdfdbc96,0xbddf3d7c,0xbdb1bdb9,0x3d153df5,0xbdac3dbe,0xbc173dff,0xbdfc3caf,
0x3db53d80,0xbdac3dbe,0x3b493e00,0xbdff3c17,0xbd15bdf5,0xbd843ddc,0x3ce03dfa,0xbdf73d09,0xbd71bde2,0xbd2c3df1,0x3d4f3dea,0xbde53d66,0xbda2bdc6,0xbc963dfd,0x3d933dd1,0xbdca3d9d,
0xbdb53d80,0x3dcebd98,0x3c17bdff,0x3dfa3ce0,0x3dc6bda2,0x3e00bbc9,0x3d9dbdca,0x3db13db9,0x3dffbc49,0x3ddc3d84,0x3df3bd21,0x3caf3dfc,0x3de23d71,0x3d5b3de7,0x3df73d09,0xbd4f3dea,
0x3db53d80,0xbde73d5b,0xbcaf3dfc,0xbddfbd7c,0x3de23d71,0xbd98bdce,0xbe003b49,0x3d21bdf3,0xbd153df5,0x3dacbdbe,0xbce0bdfa,0x3dfe3c7b,0xbdffbc49,0x3ddc3d84,0x3deabd4f,0x3c173dff,
0xbdb53d80,0x3df8bcf9,0x3d09bdf7,0x3db13db9,0xbc493dff,0xbd2c3df1,0x3da73dc2,0xbdfc3caf,0xbdc6bda2,0xbd98bdce,0xbdfe3c7b,0x3d4fbdea,0x3df5bd15,0x3e00bbc9,0x3d66bde5,0x3d893dd8,
0x3db53d80,0xbe003bc9,0xbd383def,0xbd66bde5,0xbdf53d15,0x3df8bcf9,0x3cafbdfc,0x3d9d3dca,0x3de2bd71,0xbde73d5b,0x3b493e00,0xbdc2bda7,0xbdc63da2,0x3dcebd98,0xbce0bdfa,0x3ddf3d7c,
0xbdb53d80,0x3dfd3c96,0x3d66bde5,0x3caf3dfc,0xbda2bdc6,0xbdbebdac,0xbddf3d7c,0x3d4fbdea,0x3c493dff,0x3cf93df8,0x3dff3c17,0xbdd83d89,0x3d71bde2,0x3d2cbdf1,0xbdcabd9d,0x3e003b49,
0x3db53d80,0xbdf1bd2c,0xbd893dd8,0x3c7bbdfe,0x3d71bde2,0xbc963dfd,0x3def3d38,0xbdff3c17,0xbdf5bd15,0x3e00bbc9,0x3cafbdfc,0x3d093df7,0xbc493dff,0xbcf9bdf8,0xbe003b49,0x3de5bd66,
0xbdb53d80,0x3ddc3d84,0x3d9dbdca,0xbd4f3dea,0x3dff3c49,0x3de7bd5b,0xbd21bdf3,0x3d893dd8,0x3da2bdc6,0x3c96bdfd,0xbdf7bd09,0x3e003b49,0xbd15bdf5,0xbdbebdac,0xbdc23da7,0x3d93bdd1,
0x3db53d80,0xbdbebdac,0xbdb13db9,0x3da7bdc2,0x3d153df5,0xbddcbd84,0xbd893dd8,0x3d7cbddf,0x3d713de2,0xbdf1bd2c,0xbd383def,0x3d21bdf3,0x3da23dc6,0xbdfdbc96,0xbcaf3dfc,0x3c7bbdfe,
0xbdb53d80,0x3d983dce,0x3dc2bda7,0xbdd83d89,0xbdc63da2,0x3bc93e00,0x3dfebc7b,0xbe00bb49,0xbdff3c49,0xbd843ddc,0x3de53d66,0xbdd1bd93,0xbde2bd71,0xbde73d5b,0x3d7c3ddf,0xbd38bdef,
0x3db53d80,0xbd5bbde7,0xbdd13d93,0x3df7bd09,0xbde2bd71,0x3dcebd98,0xbdb9bdb1,0x3d663de5,0x3d15bdf5,0x3dbe3dac,0x3d89bdd8,0xbdca3d9d,0x3dff3c49,0xbd843ddc,0x3def3d38,0xbdc2bda7,
0xbdb53d80,0x3cf93df8,0x3ddfbd7c,0xbe00bb49,0x3c49bdff,0xbdf1bd2c,0xbc173dff,0x3d93bdd1,0x3dc63da2,0x3dcebd98,0xbdcabd9d,0x3d383def,0xbdf53d15,0x3bc93e00,0x3df3bd21,0xbdfabce0,
0x3db53d80,0xbbc9be00,0xbdea3d4f,0x3df33d21,0x3df5bd15,0x3cf93df8,0x3dd1bd93,0xbdfebc7b,0xbde23d71,0xbd5bbde7,0xbdb13db9,0x3dffbc17,0x3dc6bda2,0x3d983dce,0x3d89bdd8,0xbdf73d09,
0xbdb53d80,0xbc963dfd,0x3df3bd21,0xbdd1bd93,0x3da23dc6,0x3dacbdbe,0xbdf7bd09,0x3d383def,0xbc49bdff,0xbdf83cf9,0x3da73dc2,0x3ce0bdfa,0xbd713de2,0x3df13d2c,0xbc7bbdfe,0xbdb93db1,
0x3db53d80,0x3d2cbdf1,0xbdfa3ce0,0x3d9d3dca,0xbd713de2,0xbdfdbc96,0x3d4f3dea,0x3da7bdc2,0x3df53d15,0x3bc93e00,0x3dd1bd93,0xbddfbd7c,0x3c49bdff,0x3df8bcf9,0xbdb9bdb1,0xbd213df3,
0xbdb53d80,0xbd843ddc,0x3dfebc7b,0xbd38bdef,0xbdffbc49,0x3d5b3de7,0x3d66bde5,0xbdfabce0,0xbda23dc6,0x3dfd3c96,0xbd7cbddf,0xbdb93db1,0x3d153df5,0x3dacbdbe,0xbdffbc17,0x3caf3dfc,
0x3db53d80,0x3dacbdbe,0xbe003b49,0x3c173dff,0xbd15bdf5,0x3d84bddc,0xbdfa3ce0,0x3d093df7,0xbd71bde2,0x3d2cbdf1,0xbdea3d4f,0x3d663de5,0xbda2bdc6,0x3c96bdfd,0xbdd13d93,0x3d9d3dca,
0xbdb53d80,0xbdce3d98,0x3dff3c17,0x3ce0bdfa,0x3dc6bda2,0xbe003bc9,0x3dca3d9d,0x3db9bdb1,0x3dffbc49,0xbddcbd84,0x3d213df3,0x3dfcbcaf,0x3de23d71,0xbd5bbde7,0xbd093df7,0x3dea3d4f,
0x3db53d80,0x3de7bd5b,0xbdfcbcaf,0xbd7c3ddf,0x3de23d71,0x3d983dce,0xbb49be00,0xbdf3bd21,0xbd153df5,0xbdac3dbe,0x3dfabce0,0x3c7bbdfe,0xbdffbc49,0xbddcbd84,0x3d4f3dea,0x3dffbc17,
0xbdb53d80,0xbdf83cf9,0x3df73d09,0x3db9bdb1,0xbc493dff,0x3d2cbdf1,0xbdc23da7,0x3caf3dfc,0xbdc6bda2,0x3d983dce,0xbc7bbdfe,0xbdeabd4f,0x3df5bd15,0xbe003bc9,0x3de53d66,0x3dd8bd89,
0x3db53d80,0x3e00bbc9,0xbdefbd38,0xbde53d66,0xbdf53d15,0xbdf83cf9,0x3dfc3caf,0x3dcabd9d,0x3de2bd71,0x3de7bd5b,0xbe003b49,0xbda73dc2,0xbdc63da2,0xbdce3d98,0x3dfabce0,0x3d7cbddf,
0xbdb53d80,0xbdfdbc96,0x3de53d66,0x3dfcbcaf,0xbda2bdc6,0x3dbe3dac,0xbd7cbddf,0xbdeabd4f,0x3c493dff,0xbcf9bdf8,0xbc173dff,0x3d893dd8,0x3d71bde2,0xbd2c3df1,0x3d9dbdca,0x3b49be00,
0x3db53d80,0x3df13d2c,0xbdd8bd89,0xbdfebc7b,0x3d71bde2,0x3c96bdfd,0xbd383def,0x3c173dff,0xbdf5bd15,0xbe003bc9,0x3dfc3caf,0x3df7bd09,0xbc493dff,0x3cf93df8,0xbb49be00,0xbd66bde5,
0xbdb53d80,0xbddcbd84,0x3dca3d9d,0x3dea3d4f,0x3dff3c49,0xbde73d5b,0x3df3bd21,0x3dd8bd89,0x3da2bdc6,0xbc963dfd,0x3d09bdf7,0x3b49be00,0xbd15bdf5,0x3dbe3dac,0xbda7bdc2,0xbdd1bd93,
0x3db53d80,0x3dbe3dac,0xbdb9bdb1,0xbdc2bda7,0x3d153df5,0x3ddc3d84,0xbdd8bd89,0xbddfbd7c,0x3d713de2,0x3df13d2c,0xbdefbd38,0xbdf3bd21,0x3da23dc6,0x3dfd3c96,0xbdfcbcaf,0xbdfebc7b,
0x3f800000,0x0,0x3f800000,0x0,0x3f800000,0x0,0x3f800000,0x0,0x3f800000,0x0,0x3f800000,0x0,0x3f800000,0x0,0x3f800000,0x0,
0x3f800000,0x0,0x3f7ffb11,0xbc490e90,0x3f7fec43,0xbcc90ab0,0x3f7fd397,0xbd16c32c,0x3f7fb10f,0xbd48fb30,0x3f7f84ab,0xbd7b2b74,0x3f7f4e6d,0xbd96a905,0x3f7f0e58,0xbdafb680,
0x3f800000,0x0,0x3f7fec43,0xbcc90ab0,0x3f7fb10f,0xbd48fb30,0x3f7f4e6d,0xbd96a905,0x3f7ec46d,0xbdc8bd36,0x3f7e1324,0xbdfab273,0x3f7d3aac,0xbe164083,0x3f7c3b28,0xbe2f10a2,
0x3f800000,0x0,0x3f7fd397,0xbd16c32c,0x3f7f4e6d,0xbd96a905,0x3f7e70b0,0xbde1bc2e,0x3f7d3aac,0xbe164083,0x3f7baccd,0xbe3b6ecf,0x3f79c79d,0xbe605c13,0x3f778bc5,0xbe827dc0,
0x3f800000,0x0,0x3f7fb10f,0xbd48fb30,0x3f7ec46d,0xbdc8bd36,0x3f7d3aac,0xbe164083,0x3f7b14be,0xbe47c5c2,0x3f7853f8,0xbe78cfcc,0x3f74fa0b,0xbe94a031,0x3f710908,0xbeac7cd4,
0x3f800000,0x0,0x3f7f84ab,0xbd7b2b74,0x3f7e1324,0xbdfab273,0x3f7baccd,0xbe3b6ecf,0x3f7853f8,0xbe78cfcc,0x3f740bdd,0xbe9aa086,0x3f6ed89e,0xbeb8442a,0x3f68bf3c,0xbed53641,
0x3f800000,0x0,0x3f7f4e6d,0xbd96a905,0x3f7d3aac,0xbe164083,0x3f79c79d,0xbe605c13,0x3f74fa0b,0xbe94a031,0x3f6ed89e,0xbeb8442a,0x3f676bd8,0xbedae880,0x3f5ebe05,0xbefc5d27,
0x3f800000,0x0,0x3f7f0e58,0xbdafb680,0x3f7c3b28,0xbe2f10a2,0x3f778bc5,0xbe827dc0,0x3f710908,0xbeac7cd4,0x3f68bf3c,0xbed53641,0x3f5ebe05,0xbefc5d27,0x3f531849,0xbf10d3cd,
0x3f800000,0x0,0x3f7b14be,0xbe47c5c2,0x3f6c835e,0xbec3ef15,0x3f54db31,0xbf0e39da,0x3f3504f3,0xbf3504f3,0x3f0e39da,0xbf54db31,0x3ec3ef15,0xbf6c835e,0x3e47c5c2,0xbf7b14be,
0x3f800000,0x0,0x3f7a7302,0xbe541501,0x3f6a09a7,0xbecf7bca,0x3f4f7a1f,0xbf15f6d9,0x3f2beb4a,0xbf3daef9,0x3f00e7e4,0xbf5d2d53,0x3ea09ae5,0xbf731447,0x3de1bc2e,0xbf7e70b0,
0x3f800000,0x0,0x3f79c79d,0xbe605c13,0x3f676bd8,0xbedae880,0x3f49d112,0xbf1d7fd1,0x3f226799,0xbf45e403,0x3ee63375,0xbf64aa59,0x3e78cfcc,0xbf7853f8,0x3cc90ab0,0xbf7fec43,
0x3f800000,0x0,0x3f791298,0xbe6c9a7f,0x3f64aa59,0xbee63375,0x3f43e200,0xbf24d225,0x3f187fc0,0xbf4d9f02,0x3ec9b953,0xbf6b4b0c,0x3e2f10a2,0xbf7c3b28,0xbd7b2b74,0xbf7f84ab,
0x3f800000,0x0,0x3f7853f8,0xbe78cfcc,0x3f61c598,0xbef15aea,0x3f3daef9,0xbf2beb4a,0x3f0e39da,0xbf54db31,0x3eac7cd4,0xbf710908,0x3dc8bd36,0xbf7ec46d,0xbe164083,0xbf7d3aac,
0x3f800000,0x0,0x3f778bc5,0xbe827dc0,0x3f5ebe05,0xbefc5d27,0x3f373a23,0xbf32c8c9,0x3f039c3d,0xbf5b941a,0x3e8e9a22,0xbf75dec6,0x3cc90ab0,0xbf7fec43,0xbe6c9a7f,0xbf791298,
0x3f800000,0x0,0x3f76ba07,0xbe888e93,0x3f5b941a,0xbf039c3d,0x3f3085bb,0xbf396842,0x3ef15aea,0xbf61c598,0x3e605c13,0xbf79c79d,0xbd48fb30,0xbf7fb10f,0xbea09ae5,0xbf731447,
0x3f800000,0x0,0x3f75dec6,0xbe8e9a22,0x3f584853,0xbf08f59b,0x3f299415,0xbf3fc767,0x3edae880,0xbf676bd8,0x3e22abb6,0xbf7cbfc9,0xbdfab273,0xbf7e1324,0xbec9b953,0xbf6b4b0c,
0x3f800000,0x0,0x3f7ec46d,0xbdc8bd36,0x3f7b14be,0xbe47c5c2,0x3f74fa0b,0xbe94a031,0x3f6c835e,0xbec3ef15,0x3f61c598,0xbef15aea,0x3f54db31,0xbf0e39da,0x3f45e403,0xbf226799,
0x3f800000,0x0,0x3f6b4b0c,0xbec9b953,0x3f3085bb,0xbf396842,0x3eb263ef,0xbf6ff573,0xbd48fb30,0xbf7fb10f,0xbee0924f,0xbf660f88,0xbf41d870,0xbf273656,0xbf740bdd,0xbe9aa086,
0x3f800000,0x0,0x3f6a09a7,0xbecf7bca,0x3f2beb4a,0xbf3daef9,0x3ea09ae5,0xbf731447,0xbdc8bd36,0xbf7ec46d,0xbefc5d27,0xbf5ebe05,0xbf4d9f02,0xbf187fc0,0xbf79c79d,0xbe605c13,
0x3f800000,0x0,0x3f68bf3c,0xbed53641,0x3f273656,0xbf41d870,0x3e8e9a22,0xbf75dec6,0xbe164083,0xbf7d3aac,0xbf0b9a6b,0xbf5695e5,0xbf584853,0xbf08f59b,0xbf7dabcc,0xbe09cf86,
0x3f800000,0x0,0x3f676bd8,0xbedae880,0x3f226799,0xbf45e403,0x3e78cfcc,0xbf7853f8,0xbe47c5c2,0xbf7b14be,0xbf187fc0,0xbf4d9f02,0xbf61c598,0xbef15aea,0xbf7fb10f,0xbd48fb30,
0x3f800000,0x0,0x3f660f88,0xbee0924f,0x3f1d7fd1,0xbf49d112,0x3e541501,0xbf7a7302,0xbe78cfcc,0xbf7853f8,0xbf24d225,0xbf43e200,0xbf6a09a7,0xbecf7bca,0xbf7fd397,0x3d16c32c,
0x3f800000,0x0,0x3f64aa59,0xbee63375,0x3f187fc0,0xbf4d9f02,0x3e2f10a2,0xbf7c3b28,0xbe94a031,0xbf74fa0b,0xbf3085bb,0xbf396842,0xbf710908,0xbeac7cd4,0xbf7e1324,0x3dfab273,
0x3f800000,0x0,0x3f633c5a,0xbeebcbbb,0x3f13682a,0xbf514d3d,0x3e09cf86,0xbf7dabcc,0xbeac7cd4,0xbf710908,0xbf3b8f3b,0xbf2e3bde,0xbf76ba07,0xbe888e93,0xbf7a7302,0x3e541501,
0x3f800000,0x0,0x3f74fa0b,0xbe94a031,0x3f54db31,0xbf0e39da,0x3f226799,0xbf45e403,0x3ec3ef15,0xbf6c835e,0x3dc8bd36,0xbf7ec46d,0xbe47c5c2,0xbf7b14be,0xbef15aea,0xbf61c598,
0x3f800000,0x0,0x3f531849,0xbf10d3cd,0x3eb8442a,0xbf6ed89e,0xbe6c9a7f,0xbf791298,0xbf3daef9,0xbf2beb4a,0xbf7dabcc,0xbe09cf86,0xbf64aa59,0x3ee63375,0xbef6e0cb,0x3f604621,
0x3f800000,0x0,0x3f514d3d,0xbf13682a,0x3eac7cd4,0xbf710908,0xbe888e93,0xbf76ba07,0xbf45e403,0xbf226799,0xbf7f4e6d,0xbd96a905,0xbf5b941a,0x3f039c3d,0xbecf7bca,0x3f6a09a7,
0x3f800000,0x0,0x3f4f7a1f,0xbf15f6d9,0x3ea09ae5,0xbf731447,0xbe9aa086,0xbf740bdd,0xbf4d9f02,0xbf187fc0,0xbf7ffb11,0xbc490e90,0xbf514d3d,0x3f13682a,0xbea68f12,0x3f721352,
0x3f800000,0x0,0x3f4d9f02,0xbf187fc0,0x3e94a031,0xbf74fa0b,0xbeac7cd4,0xbf710908,0xbf54db31,0xbf0e39da,0xbf7fb10f,0x3d48fb30,0xbf45e403,0x3f226799,0xbe78cfcc,0x3f7853f8,
0x3f800000,0x0,0x3f4bbbf8,0xbf1b02c6,0x3e888e93,0xbf76ba07,0xbebe1d4a,0xbf6db293,0xbf5b941a,0xbf039c3d,0xbf7e70b0,0x3de1bc2e,0xbf396842,0x3f3085bb,0xbe22abb6,0x3f7cbfc9,
0x3f800000,0x0,0x3f49d112,0xbf1d7fd1,0x3e78cfcc,0xbf7853f8,0xbecf7bca,0xbf6a09a7,0xbf61c598,0xbef15aea,0xbf7c3b28,0x3e2f10a2,0xbf2beb4a,0x3f3daef9,0xbd96a905,0x3f7f4e6d,
0x3f800000,0x0,0x3f47de65,0xbf1ff6cb,0x3e605c13,0xbf79c79d,0xbee0924f,0xbf660f88,0xbf676bd8,0xbedae880,0xbf791298,0x3e6c9a7f,0xbf1d7fd1,0x3f49d112,0x3c490e90,0x3f7ffb11,
0x3f800000,0x0,0x3f800000,0x0,0x3f800000,0x0,0x3f800000,0x0,0x40000000,0x0,0x3f800000,0x0,0x3f800000,0x0,0x3f800000,0x0,
0x3f800000,0x0,0x3f7ffb11,0xbc490e90,0x3f7fec43,0xbcc90ab0,0x3f7fd397,0xbd16c32c,0x3fffb10f,0xbdc8fb30,0x3f7f84ab,0xbd7b2b74,0x3f7f4e6d,0xbd96a905,0x3f7f0e58,0xbdafb680,
0x3f800000,0x0,0x3f7fec43,0xbcc90ab0,0x3f7fb10f,0xbd48fb30,0x3f7f4e6d,0xbd96a905,0x3ffec46d,0xbe48bd36,0x3f7e1324,0xbdfab273,0x3f7d3aac,0xbe164083,0x3f7c3b28,0xbe2f10a2,
0x3f800000,0x0,0x3f7fd397,0xbd16c32c,0x3f7f4e6d,0xbd96a905,0x3f7e70b0,0xbde1bc2e,0x3ffd3aac,0xbe964083,0x3f7baccd,0xbe3b6ecf,0x3f79c79d,0xbe605c13,0x3f778bc5,0xbe827dc0,
0x3f800000,0x0,0x3f7fb10f,0xbd48fb30,0x3f7ec46d,0xbdc8bd36,0x3f7d3aac,0xbe164083,0x3ffb14be,0xbec7c5c2,0x3f7853f8,0xbe78cfcc,0x3f74fa0b,0xbe94a031,0x3f710908,0xbeac7cd4,
0x3f800000,0x0,0x3f7f84ab,0xbd7b2b74,0x3f7e1324,0xbdfab273,0x3f7baccd,0xbe3b6ecf,0x3ff853f8,0xbef8cfcc,0x3f740bdd,0xbe9aa086,0x3f6ed89e,0xbeb8442a,0x3f68bf3c,0xbed53641,
0x3f800000,0x0,0x3f7f4e6d,0xbd96a905,0x3f7d3aac,0xbe164083,0x3f79c79d,0xbe605c13,0x3ff4fa0b,0xbf14a031,0x3f6ed89e,0xbeb8442a,0x3f676bd8,0xbedae880,0x3f5ebe05,0xbefc5d27,
0x3f800000,0x0,0x3f7f0e58,0xbdafb680,0x3f7c3b28,0xbe2f10a2,0x3f778bc5,0xbe827dc0,0x3ff10908,0xbf2c7cd4,0x3f68bf3c,0xbed53641,0x3f5ebe05,0xbefc5d27,0x3f531849,0xbf10d3cd,
0x3f800000,0x0,0x3f7ec46d,0xbdc8bd36,0x3f7b14be,0xbe47c5c2,0x3f74fa0b,0xbe94a031,0x3fec835e,0xbf43ef15,0x3f61c598,0xbef15aea,0x3f54db31,0xbf0e39da,0x3f45e403,0xbf226799,
0x3f800000,0x0,0x3f7e70b0,0xbde1bc2e,0x3f79c79d,0xbe605c13,0x3f721352,0xbea68f12,0x3fe76bd8,0xbf5ae880,0x3f59f26a,0xbf064b82,0x3f49d112,0xbf1d7fd1,0x3f373a23,0xbf32c8c9,
0x3f800000,0x0,0x3f7e1324,0xbdfab273,0x3f7853f8,0xbe78cfcc,0x3f6ed89e,0xbeb8442a,0x3fe1c598,0xbf715aea,0x3f514d3d,0xbf13682a,0x3f3daef9,0xbf2beb4a,0x3f273656,0xbf41d870,
0x3f800000,0x0,0x3f7dabcc,0xbe09cf86,0x3f76ba07,0xbe888e93,0x3f6b4b0c,0xbec9b953,0x3fdb941a,0xbf839c3d,0x3f47de65,0xbf1ff6cb,0x3f3085bb,0xbf396842,0x3f15f6d9,0xbf4f7a1f,
0x3f800000,0x0,0x3f7d3aac,0xbe164083,0x3f74fa0b,0xbe94a031,0x3f676bd8,0xbedae880,0x3fd4db31,0xbf8e39da,0x3f3daef9,0xbf2beb4a,0x3f226799,0xbf45e403,0x3f039c3d,0xbf5b941a,
0x3f800000,0x0,0x3f7cbfc9,0xbe22abb6,0x3f731447,0xbea09ae5,0x3f633c5a,0xbeebcbbb,0x3fcd9f02,0xbf987fc0,0x3f32c8c9,0xbf373a23,0x3f13682a,0xbf514d3d,0x3ee0924f,0xbf660f88,
0x3f800000,0x0,0x3f7c3b28,0xbe2f10a2,0x3f710908,0xbeac7cd4,0x3f5ebe05,0xbefc5d27,0x3fc5e403,0xbfa26799,0x3f273656,0xbf41d870,0x3f039c3d,0xbf5b941a,0x3eb8442a,0xbf6ed89e,
0x3f800000,0x0,0x3f7baccd,0xbe3b6ecf,0x3f6ed89e,0xbeb8442a,0x3f59f26a,0xbf064b82,0x3fbdaef9,0xbfabeb4a,0x3f1b02c6,0xbf4bbbf8,0x3ee63375,0xbf64aa59,0x3e8e9a22,0xbf75dec6,
0x3f800000,0x0,0x3f7b14be,0xbe47c5c2,0x3f6c835e,0xbec3ef15,0x3f54db31,0xbf0e39da,0x3fb504f3,0xbfb504f3,0x3f0e39da,0xbf54db31,0x3ec3ef15,0xbf6c835e,0x3e47c5c2,0xbf7b14be,
0x3f800000,0x0,0x3f7a7302,0xbe541501,0x3f6a09a7,0xbecf7bca,0x3f4f7a1f,0xbf15f6d9,0x3fabeb4a,0xbfbdaef9,0x3f00e7e4,0xbf5d2d53,0x3ea09ae5,0xbf731447,0x3de1bc2e,0xbf7e70b0,
0x3f800000,0x0,0x3f79c79d,0xbe605c13,0x3f676bd8,0xbedae880,0x3f49d112,0xbf1d7fd1,0x3fa26799,0xbfc5e403,0x3ee63375,0xbf64aa59,0x3e78cfcc,0xbf7853f8,0x3cc90ab0,0xbf7fec43,
0x3f800000,0x0,0x3f791298,0xbe6c9a7f,0x3f64aa59,0xbee63375,0x3f43e200,0xbf24d225,0x3f987fc0,0xbfcd9f02,0x3ec9b953,0xbf6b4b0c,0x3e2f10a2,0xbf7c3b28,0xbd7b2b74,0xbf7f84ab,
0x3f800000,0x0,0x3f7853f8,0xbe78cfcc,0x3f61c598,0xbef15aea,0x3f3daef9,0xbf2beb4a,0x3f8e39da,0xbfd4db31,0x3eac7cd4,0xbf710908,0x3dc8bd36,0xbf7ec46d,0xbe164083,0xbf7d3aac,
0x3f800000,0x0,0x3f778bc5,0xbe827dc0,0x3f5ebe05,0xbefc5d27,0x3f373a23,0xbf32c8c9,0x3f839c3d,0xbfdb941a,0x3e8e9a22,0xbf75dec6,0x3cc90ab0,0xbf7fec43,0xbe6c9a7f,0xbf791298,
0x3f800000,0x0,0x3f76ba07,0xbe888e93,0x3f5b941a,0xbf039c3d,0x3f3085bb,0xbf396842,0x3f715aea,0xbfe1c598,0x3e605c13,0xbf79c79d,0xbd48fb30,0xbf7fb10f,0xbea09ae5,0xbf731447,
0x3f800000,0x0,0x3f75dec6,0xbe8e9a22,0x3f584853,0xbf08f59b,0x3f299415,0xbf3fc767,0x3f5ae880,0xbfe76bd8,0x3e22abb6,0xbf7cbfc9,0xbdfab273,0xbf7e1324,0xbec9b953,0xbf6b4b0c,
0x3f800000,0x0,0x3f74fa0b,0xbe94a031,0x3f54db31,0xbf0e39da,0x3f226799,0xbf45e403,0x3f43ef15,0xbfec835e,0x3dc8bd36,0xbf7ec46d,0xbe47c5c2,0xbf7b14be,0xbef15aea,0xbf61c598,
0x3f800000,0x0,0x3f740bdd,0xbe9aa086,0x3f514d3d,0xbf13682a,0x3f1b02c6,0xbf4bbbf8,0x3f2c7cd4,0xbff10908,0x3d16c32c,0xbf7fd397,0xbe888e93,0xbf76ba07,0xbf0b9a6b,0xbf5695e5,
0x3f800000,0x0,0x3f731447,0xbea09ae5,0x3f4d9f02,0xbf187fc0,0x3f13682a,0xbf514d3d,0x3f14a031,0xbff4fa0b,0xbcc90ab0,0xbf7fec43,0xbeac7cd4,0xbf710908,0xbf1d7fd1,0xbf49d112,
0x3f800000,0x0,0x3f721352,0xbea68f12,0x3f49d112,0xbf1d7fd1,0x3f0b9a6b,0xbf5695e5,0x3ef8cfcc,0xbff853f8,0xbdafb680,0xbf7f0e58,0xbecf7bca,0xbf6a09a7,0xbf2e3bde,0xbf3b8f3b,
0x3f800000,0x0,0x3f710908,0xbeac7cd4,0x3f45e403,0xbf226799,0x3f039c3d,0xbf5b941a,0x3ec7c5c2,0xbffb14be,0xbe164083,0xbf7d3aac,0xbef15aea,0xbf61c598,0xbf3daef9,0xbf2beb4a,
0x3f800000,0x0,0x3f6ff573,0xbeb263ef,0x3f41d870,0xbf273656,0x3ef6e0cb,0xbf604621,0x3e964083,0xbffd3aac,0xbe541501,0xbf7a7302,0xbf08f59b,0xbf584853,0xbf4bbbf8,0xbf1b02c6,
0x3f800000,0x0,0x3f6ed89e,0xbeb8442a,0x3f3daef9,0xbf2beb4a,0x3ee63375,0xbf64aa59,0x3e48bd36,0xbffec46d,0xbe888e93,0xbf76ba07,0xbf187fc0,0xbf4d9f02,0xbf584853,0xbf08f59b,
0x3f800000,0x0,0x3f6db293,0xbebe1d4a,0x3f396842,0xbf3085bb,0x3ed53641,0xbf68bf3c,0x3dc8fb30,0xbfffb10f,0xbea68f12,0xbf721352,0xbf273656,0xbf41d870,0xbf633c5a,0xbeebcbbb,
0x3f800000,0x0,0x3f7fffb1,0xbb490fc6,0x3f7ffec4,0xbbc90f88,0x3f7ffd39,0xbc16cb58,0x3ffffb11,0xbcc90e90,0x3f7ff84a,0xbc7b514b,0x3f7ff4e6,0xbc96c9b6,0x3f7ff0e3,0xbcafea69,
0x3f800000,0x0,0x3f7ff84a,0xbc7b514b,0x3f7fe129,0xbcfb49ba,0x3f7fba9e,0xbd3c6dd5,0x3fff84ab,0xbdfb2b74,0x3f7f3f54,0xbd9cecf9,0x3f7eea9d,0xbdbc3ac3,0x3f7e868b,0xbddb7d37,
0x3f800000,0x0,0x3f7fe705,0xbce22a7a,0x3f7f9c18,0xbd621469,0x3f7f1f49,0xbda973ba,0x3ffe70b0,0xbe61bc2e,0x3f7d906e,0xbe0cec4a,0x3f7c7eb0,0xbe28defc,0x3f7b3bab,0xbe44b0b9,
0x3f800000,0x0,0x3f7fcbe2,0xbd2351cb,0x3f7f2f9d,0xbda3308c,0x3f7e2b72,0xbdf475c0,0x3ffcbfc9,0xbea2abb6,0x3f7aed37,0xbe4ada4f,0x3f78b47b,0xbe72b651,0x3f76167a,0xbe8d17c0,
0x3f800000,0x0,0x3f7fa6e3,0xbd55880e,0x3f7e9bc9,0xbdd53db9,0x3f7cdf6c,0xbe1f917b,0x3ffa7302,0xbed41501,0x3f77583a,0xbe840270,0x3f73913f,0xbe9d9e78,0x3f6f20b0,0xbeb6ccc3,
0x3f800000,0x0,0x3f7f7808,0xbd83db0a,0x3f7de0b1,0xbe039502,0x3f7b3bab,0xbe44b0b9,0x3ff78bc5,0xbf027dc0,0x3f72d4eb,0xbea21887,0x3f6d1c1d,0xbec1071e,0x3f666771,0xbedf28a9,
0x3f800000,0x0,0x3f7f3f54,0xbd9cecf9,0x3f7cfe73,0xbe1c76de,0x3f7940c0,0xbe698bba,0x3ff40bdd,0xbf1aa086,0x3f6d67a1,0xbebf926f,0x3f655e0b,0xbee363fa,0x3f5bfb34,0xbf02ef9f,
0x3f800000,0x0,0x3f7efcc9,0xbdb5f8da,0x3f7bf531,0xbe354098,0x3f76ef5b,0xbe870ada,0x3feff573,0xbf3263ef,0x3f671599,0xbedc53c1,0x3f5c61c7,0xbf0242b1,0x3f4fefa8,0xbf1553b7,
0x3f800000,0x0,0x3f7eb069,0xbdcefdb7,0x3f7ac516,0xbe4dee60,0x3f74484b,0xbe9920fe,0x3feb4b0c,0xbf49b953,0x3f5fe4e9,0xbef840c8,0x3f5233c6,0xbf121eb0,0x3f425b89,0xbf269de3,
0x3f800000,0x0,0x3f7e5a38,0xbde7fa9a,0x3f796e4e,0xbe667c66,0x3f714c7a,0xbeab0201,0x3fe60f88,0xbf60924f,0x3f57dc7f,0xbf099f4e,0x3f46e22a,0xbf212ff9,0x3f33587a,0xbf36ad7f,
0x3f800000,0x0,0x3f7dfa38,0xbe007745,0x3f77f110,0xbe7ee6e1,0x3f6dfcf2,0xbebca7af,0x3fe04621,0xbf76e0cb,0x3f4f0417,0xbf16999f,0x3f3a7ca4,0xbf2f61a5,0x3f2302d3,0xbf456439,
0x3f800000,0x0,0x3f7d906e,0xbe0cec4a,0x3f764d97,0xbe8b9507,0x3f6a5ad9,0xbece0bea,0x3fd9f26a,0xbf864b82,0x3f456439,0xbf2302d3,0x3f2d1469,0xbf3ca003,0x3f11796b,0xbf52a649,
0x3f800000,0x0,0x3f7d1cdd,0xbe195be0,0x3f748422,0xbe97a117,0x3f666771,0xbedf28a9,0x3fd31849,0xbf90d3cd,0x3f3b0629,0xbf2ecef7,0x3f1ebc12,0xbf48d8b3,0x3efdbabb,0xbf5e5aa6,
0x3f800000,0x0,0x3f7c9f8a,0xbe25c58c,0x3f7294f8,0xbea395c5,0x3f62241a,0xbeeff7fb,0x3fcbbbf8,0xbf9b02c6,0x3f2ff3e6,0xbf39f2ac,0x3f0f8784,0xbf53fac3,0x3ed6a399,0xbf686b39,
0x3f800000,0x0,0x3f7c187a,0xbe3228d4,0x3f708066,0xbeaf713a,0x3f5d924d,0xbf003a06,0x3fc3e200,0xbfa4d225,0x3f24381a,0xbf446337,0x3eff17b2,0xbf5df6be,0x3eadf73c,0xbf70c501,
0x3f800000,0x0,0x3f7b87b2,0xbe3e853e,0x3f6e46be,0xbebb31a0,0x3f58b3a1,0xbf084b92,0x3fbb8f3b,0xbfae3bde,0x3f17de12,0xbf4e1689,0x3eddbe79,0xbf66becc,0x3e840270,0xbf77583a,
0x3f800000,0x0,0x3f7aed37,0xbe4ada4f,0x3f6be858,0xbec6d529,0x3f5389c7,0xbf102dd5,0x3fb2c8c9,0xbfb73a23,0x3f0af1b7,0xbf570348,0x3ebb31a0,0xbf6e46be,0x3e3228d4,0xbf7c187a,
0x3f800000,0x0,0x3f7a4910,0xbe57278f,0x3f696591,0xbed25a09,0x3f4e1689,0xbf17de12,0x3fa99415,0xbfbfc767,0x3efafef7,0xbf5f20db,0x3e97a117,0xbf748422,0x3db5f8da,0xbf7efcc9,
0x3f800000,0x0,0x3f799b43,0xbe636c83,0x3f66becc,0xbeddbe79,0x3f485bca,0xbf1f599f,0x3f9ff6cb,0xbfc7de65,0x3edf28a9,0xbf666771,0x3e667c66,0xbf796e4e,0x3b490fc6,0xbf7fffb1,
0x3f800000,0x0,0x3f78e3d6,0xbe6fa8b2,0x3f63f473,0xbee900b7,0x3f425b89,0xbf269de3,0x3f95f6d9,0xbfcf7a1f,0x3ec27b55,0xbf6cd007,0x3e1c76de,0xbf7cfe73,0xbda973ba,0xbf7f1f49,
0x3f800000,0x0,0x3f7822d1,0xbe7bdba4,0x3f6106f2,0xbef41f07,0x3f3c17d9,0xbf2da859,0x3f8b9a6b,0xbfd695e5,0x3ea5129f,0xbf725470,0x3da3308c,0xbf7f2f9d,0xbe2bf804,0xbf7c5d3a,
0x3f800000,0x0,0x3f77583a,0xbe840270,0x3f5df6be,0xbeff17b2,0x3f3592e7,0xbf34768f,0x3f80e7e4,0xbfdd2d53,0x3e870ada,0xbf76ef5b,0x3bc90f88,0xbf7ffec4,0xbe80f8c0,0xbf77beb7,
0x3f800000,0x0,0x3f76841b,0xbe8a11f7,0x3f5ac450,0xbf04f484,0x3f2ecef7,0xbf3b0629,0x3f6bcbbb,0xbfe33c5a,0x3e5101f1,0xbf7a9c59,0xbd8a200a,0xbf7f6ac7,0xbeab0201,0xbf714c7a,
0x3f800000,0x0,0x3f75a67b,0xbe901c2c,0x3f577026,0xbf0a48ad,0x3f27ce61,0xbf4154e1,0x3f553641,0xbfe8bf3c,0x3e1324ca,0xbf7d57de,0xbe1008b7,0xbf7d7474,0xbed3c867,0xbf6912ae,
0x3f800000,0x0,0x3f74bf62,0xbe9620d2,0x3f53fac3,0xbf0f8784,0x3f209393,0xbf476085,0x3f3e1d4a,0xbfedb293,0x3da973ba,0xbf7f1f49,0xbe5a3997,0xbf7a1e84,0xbefafef7,0xbf5f20db,
0x3f800000,0x0,0x3f73ced9,0xbe9c1faf,0x3f5064af,0xbf14b039,0x3f19210f,0xbf4d26fd,0x3f268f12,0xbff21352,0x3cafea69,0xbf7ff0e3,0xbe919ddd,0xbf756d97,0xbf102dd5,0xbf5389c7,
0x3f800000,0x0,0x3f72d4eb,0xbea21887,0x3f4cae79,0xbf19c200,0x3f11796b,0xbf52a649,0x3f0e9a22,0xbff5dec6,0xbd2351cb,0xbf7fcbe2,0xbeb554ec,0xbf6f6830,0xbf21cbfb,0xbf466354,
0x3f800000,0x0,0x3f71d19f,0xbea80b1f,0x3f48d8b3,0xbf1ebc12,0x3f099f4e,0xbf57dc7f,0x3eec9a7f,0xbff91298,0xbdcefdb7,0xbf7eb069,0xbed8106b,0xbf6816a8,0xbf3238aa,0xbf37c655,
0x3f800000,0x0,0x3f70c501,0xbeadf73c,0x3f44e3f5,0xbf239da9,0x3f019573,0xbf5cc7d1,0x3ebb6ecf,0xbffbaccd,0xbe25c58c,0xbf7c9f8a,0xbef9a02d,0xbf5f8327,0xbf4154e1,0xbf27ce61,
0x3f800000,0x0,0x3f6faf1b,0xbeb3dca5,0x3f40d0da,0xbf286605,0x3ef2bd43,0xbf61668a,0x3e89cf86,0xbffdabcc,0xbe636c83,0xbf799b43,0xbf0cead0,0xbf55b993,0xbf4f0417,0xbf16999f,
0x3f800000,0x0,0x3f6e8ff8,0xbeb9bb1e,0x3f3ca003,0xbf2d1469,0x3ee1fb6a,0xbf65b710,0x3e2fb680,0xbfff0e58,0xbe901c2c,0xbf75a67b,0xbf1c420c,0xbf4ac77f,0xbf5b2c79,0xbf044889,
0x3f800000,0x0,0x3f6d67a1,0xbebf926f,0x3f385216,0xbf31a81d,0x3ed0eb2a,0xbf69b7e4,0x3d96c32c,0xbfffd397,0xbeadf73c,0xbf70c501,0xbf2ac082,0xbf3ebc1b,0xbf65b710,0xbee1fb6a,
0x3f800000,0x0,0x3f7ffec4,0xbbc90f88,0x3f7ffb11,0xbc490e90,0x3f7ff4e6,0xbc96c9b6,0x3fffec43,0xbd490ab0,0x3f7fe129,0xbcfb49ba,0x3f7fd397,0xbd16c32c,0x3f7fc38f,0xbd2fe007,
0x3f800000,0x0,0x3f7ff4e6,0xbc96c9b6,0x3f7fd397,0xbd16c32c,0x3f7f9c18,0xbd621469,0x3fff4e6d,0xbe16a905,0x3f7eea9d,0xbdbc3ac3,0x3f7e70b0,0xbde1bc2e,0x3f7de0b1,0xbe039502,
0x3f800000,0x0,0x3f7fe129,0xbcfb49ba,0x3f7f84ab,0xbd7b2b74,0x3f7eea9d,0xbdbc3ac3,0x3ffe1324,0xbe7ab273,0x3f7cfe73,0xbe1c76de,0x3f7baccd,0xbe3b6ecf,0x3f7a1e84,0xbe5a3997,
0x3f800000,0x0,0x3f7fc38f,0xbd2fe007,0x3f7f0e58,0xbdafb680,0x3f7de0b1,0xbe039502,0x3ffc3b28,0xbeaf10a2,0x3f7a1e84,0xbe5a3997,0x3f778bc5,0xbe827dc0,0x3f748422,0xbe97a117,
0x3f800000,0x0,0x3f7f9c18,0xbd621469,0x3f7e70b0,0xbde1bc2e,0x3f7c7eb0,0xbe28defc,0x3ff9c79d,0xbee05c13,0x3f764d97,0xbe8b9507,0x3f721352,0xbea68f12,0x3f6d1c1d,0xbec1071e,
0x3f800000,0x0,0x3f7f6ac7,0xbd8a200a,0x3f7dabcc,0xbe09cf86,0x3f7ac516,0xbe4dee60,0x3ff6ba07,0xbf088e93,0x3f718f57,0xbea986c4,0x3f6b4b0c,0xbec9b953,0x3f63f473,0xbee900b7,
0x3f800000,0x0,0x3f7f2f9d,0xbda3308c,0x3f7cbfc9,0xbe22abb6,0x3f78b47b,0xbe72b651,0x3ff31447,0xbf209ae5,0x3f6be858,0xbec6d529,0x3f633c5a,0xbeebcbbb,0x3f591e6a,0xbf07a136,
0x3f800000,0x0,0x3f7eea9d,0xbdbc3ac3,0x3f7baccd,0xbe3b6ecf,0x3f764d97,0xbe8b9507,0x3feed89e,0xbf38442a,0x3f655e0b,0xbee363fa,0x3f59f26a,0xbf064b82,0x3f4cae79,0xbf19c200,
0x3f800000,0x0,0x3f7e9bc9,0xbdd53db9,0x3f7a7302,0xbe541501,0x3f73913f,0xbe9d9e78,0x3fea09a7,0xbf4f7bca,0x3f5df6be,0xbeff17b2,0x3f4f7a1f,0xbf15f6d9,0x3f3ebc1b,0xbf2ac082,
0x3f800000,0x0,0x3f7e4323,0xbdee3876,0x3f791298,0xbe6c9a7f,0x3f708066,0xbeaf713a,0x3fe4aa59,0xbf663375,0x3f55b993,0xbf0cead0,0x3f43e200,0xbf24d225,0x3f2f61a5,0xbf3a7ca4,
0x3f800000,0x0,0x3f7de0b1,0xbe039502,0x3f778bc5,0xbe827dc0,0x3f6d1c1d,0xbec1071e,0x3fdebe05,0xbf7c5d27,0x3f4cae79,0xbf19c200,0x3f373a23,0xbf32c8c9,0x3f1ebc12,0xbf48d8b3,
0x3f800000,0x0,0x3f7d7474,0xbe1008b7,0x3f75dec6,0xbe8e9a22,0x3f696591,0xbed25a09,0x3fd84853,0xbf88f59b,0x3f42de29,0xbf26050a,0x3f299415,0xbf3fc767,0x3f0cead0,0xbf55b993,
0x3f800000,0x0,0x3f7cfe73,0xbe1c76de,0x3f740bdd,0xbe9aa086,0x3f655e0b,0xbee363fa,0x3fd14d3d,0xbf93682a,0x3f385216,0xbf31a81d,0x3f1b02c6,0xbf4bbbf8,0x3ef41f07,0xbf6106f2,
0x3f800000,0x0,0x3f7c7eb0,0xbe28defc,0x3f721352,0xbea68f12,0x3f6106f2,0xbef41f07,0x3fc9d112,0xbf9d7fd1,0x3f2d1469,0xbf3ca003,0x3f0b9a6b,0xbf5695e5,0x3ecc9b8b,0xbf6aab7b,
0x3f800000,0x0,0x3f7bf531,0xbe354098,0x3f6ff573,0xbeb263ef,0x3f5c61c7,0xbf0242b1,0x3fc1d870,0xbfa73656,0x3f212ff9,0xbf46e22a,0x3ef6e0cb,0xbf604621,0x3ea395c5,0xbf7294f8,
0x3f800000,0x0,0x3f7b61fc,0xbe419b37,0x3f6db293,0xbebe1d4a,0x3f577026,0xbf0a48ad,0x3fb96842,0xbfb085bb,0x3f14b039,0xbf5064af,0x3ed53641,0xbf68bf3c,0x3e72b651,0xbf78b47b,
0x3f800000,0x0,0x3f7ac516,0xbe4dee60,0x3f6b4b0c,0xbec9b953,0x3f5233c6,0xbf121eb0,0x3fb085bb,0xbfb96842,0x3f07a136,0xbf591e6a,0x3eb263ef,0xbf6ff573,0x3e1c76de,0xbf7cfe73,
0x3f800000,0x0,0x3f7a1e84,0xbe5a3997,0x3f68bf3c,0xbed53641,0x3f4cae79,0xbf19c200,0x3fa73656,0xbfc1d870,0x3ef41f07,0xbf6106f2,0x3e8e9a22,0xbf75dec6,0x3d8a200a,0xbf7f6ac7,
0x3f800000,0x0,0x3f796e4e,0xbe667c66,0x3f660f88,0xbee0924f,0x3f46e22a,0xbf212ff9,0x3f9d7fd1,0xbfc9d112,0x3ed8106b,0xbf6816a8,0x3e541501,0xbf7a7302,0xbc96c9b6,0xbf7ff4e6,
0x3f800000,0x0,0x3f78b47b,0xbe72b651,0x3f633c5a,0xbeebcbbb,0x3f40d0da,0xbf286605,0x3f93682a,0xbfd14d3d,0x3ebb31a0,0xbf6e46be,0x3e09cf86,0xbf7dabcc,0xbdd53db9,0xbf7e9bc9,
0x3f800000,0x0,0x3f77f110,0xbe7ee6e1,0x3f604621,0xbef6e0cb,0x3f3a7ca4,0xbf2f61a5,0x3f88f59b,0xbfd84853,0x3e9d9e78,0xbf73913f,0x3d7b2b74,0xbf7f84ab,0xbe419b37,0xbf7b61fc,
0x3f800000,0x0,0x3f772417,0xbe8586ce,0x3f5d2d53,0xbf00e7e4,0x3f33e7bc,0xbf36206c,0x3f7c5d27,0xbfdebe05,0x3e7ee6e1,0xbf77f110,0xbc490e90,0xbf7ffb11,0xbe8b9507,0xbf764d97,
0x3f800000,0x0,0x3f764d97,0xbe8b9507,0x3f59f26a,0xbf064b82,0x3f2d1469,0xbf3ca003,0x3f663375,0xbfe4aa59,0x3e419b37,0xbf7b61fc,0xbdafb680,0xbf7f0e58,0xbeb554ec,0xbf6f6830,
0x3f800000,0x0,0x3f756d97,0xbe919ddd,0x3f5695e5,0xbf0b9a6b,0x3f26050a,0xbf42de29,0x3f4f7bca,0xbfea09a7,0x3e039502,0xbf7de0b1,0xbe22abb6,0xbf7cbfc9,0xbeddbe79,0xbf66becc,
0x3f800000,0x0,0x3f748422,0xbe97a117,0x3f531849,0xbf10d3cd,0x3f1ebc12,0xbf48d8b3,0x3f38442a,0xbfeed89e,0x3d8a200a,0xbf7f6ac7,0xbe6c9a7f,0xbf791298,0xbf0242b1,0xbf5c61c7,
0x3f800000,0x0,0x3f73913f,0xbe9d9e78,0x3f4f7a1f,0xbf15f6d9,0x3f173c07,0xbf4e8d90,0x3f209ae5,0xbff31447,0x3bc90f88,0xbf7ffec4,0xbe9aa086,0xbf740bdd,0xbf14b039,0xbf5064af,
0x3f800000,0x0,0x3f7294f8,0xbea395c5,0x3f4bbbf8,0xbf1b02c6,0x3f0f8784,0xbf53fac3,0x3f088e93,0xbff6ba07,0xbd621469,0xbf7f9c18,0xbebe1d4a,0xbf6db293,0xbf26050a,0xbf42de29,
0x3f800000,0x0,0x3f718f57,0xbea986c4,0x3f47de65,0xbf1ff6cb,0x3f07a136,0xbf591e6a,0x3ee05c13,0xbff9c79d,0xbdee3876,0xbf7e4323,0xbee0924f,0xbf660f88,0xbf36206c,0xbf33e7bc,
0x3f800000,0x0,0x3f708066,0xbeaf713a,0x3f43e200,0xbf24d225,0x3eff17b2,0xbf5df6be,0x3eaf10a2,0xbffc3b28,0xbe354098,0xbf7bf531,0xbf00e7e4,0xbf5d2d53,0xbf44e3f5,0xbf239da9,
0x3f800000,0x0,0x3f6f6830,0xbeb554ec,0x3f3fc767,0xbf299415,0x3eee9479,0xbf628210,0x3e7ab273,0xbffe1324,0xbe72b651,0xbf78b47b,0xbf10d3cd,0xbf531849,0xbf5233c6,0xbf121eb0,
0x3f800000,0x0,0x3f6e46be,0xbebb31a0,0x3f3b8f3b,0xbf2e3bde,0x3eddbe79,0xbf66becc,0x3e16a905,0xbfff4e6d,0xbe97a117,0xbf748422,0xbf1ff6cb,0xbf47de65,0xbf5df6be,0xbeff17b2,
0x3f800000,0x0,0x3f6d1c1d,0xbec1071e,0x3f373a23,0xbf32c8c9,0x3ecc9b8b,0xbf6aab7b,0x3d490ab0,0xbfffec43,0xbeb554ec,0xbf6f6830,0xbf2e3bde,0xbf3b8f3b,0xbf6816a8,0xbed8106b,
0x3f800000,0x0,0x3f7ffd39,0xbc16cb58,0x3f7ff4e6,0xbc96c9b6,0x3f7fe705,0xbce22a7a,0x3fffd397,0xbd96c32c,0x3f7fba9e,0xbd3c6dd5,0x3f7f9c18,0xbd621469,0x3f7f7808,0xbd83db0a,
0x3f800000,0x0,0x3f7ff0e3,0xbcafea69,0x3f7fc38f,0xbd2fe007,0x3f7f7808,0xbd83db0a,0x3fff0e58,0xbe2fb680,0x3f7e868b,0xbddb7d37,0x3f7de0b1,0xbe039502,0x3f7d1cdd,0xbe195be0,
0x3f800000,0x0,0x3f7fdaaf,0xbd0a342f,0x3f7f6ac7,0xbd8a200a,0x3f7eb069,0xbdcefdb7,0x3ffdabcc,0xbe89cf86,0x3f7c5d3a,0xbe2bf804,0x3f7ac516,0xbe4dee60,0x3f78e3d6,0xbe6fa8b2,
0x3f800000,0x0,0x3f7fba9e,0xbd3c6dd5,0x3f7eea9d,0xbdbc3ac3,0x3f7d906e,0xbe0cec4a,0x3ffbaccd,0xbebb6ecf,0x3f7940c0,0xbe698bba,0x3f764d97,0xbe8b9507,0x3f72d4eb,0xbea21887,
0x3f800000,0x0,0x3f7f90b1,0xbd6ea038,0x3f7e4323,0xbdee3876,0x3f7c187a,0xbe3228d4,0x3ff91298,0xbeec9a7f,0x3f75341d,0xbe931f35,0x3f708066,0xbeaf713a,0x3f6afb8c,0xbecb2aae,
0x3f800000,0x0,0x3f7f5ce9,0xbd9064b4,0x3f7d7474,0xbe1008b7,0x3f7a4910,0xbe57278f,0x3ff5dec6,0xbf0e9a22,0x3f703b37,0xbeb0eacb,0x3f696591,0xbed25a09,0x3f61668a,0xbef2bd43,
0x3f800000,0x0,0x3f7f1f49,0xbda973ba,0x3f7c7eb0,0xbe28defc,0x3f7822d1,0xbe7bdba4,0x3ff21352,0xbf268f12,0x3f6a5ad9,0xbece0bea,0x3f6106f2,0xbef41f07,0x3f5627fe,0xbf0c42c9,
0x3f800000,0x0,0x3f7ed7d4,0xbdc27c39,0x3f7b61fc,0xbe419b37,0x3f75a67b,0xbe901c2c,0x3fedb293,0xbf3e1d4a,0x3f6398ac,0xbeea6681,0x3f577026,0xbf0a48ad,0x3f495521,0xbf1e1e22,
0x3f800000,0x0,0x3f7e868b,0xbddb7d37,0x3f7a1e84,0xbe5a3997,0x3f72d4eb,0xbea21887,0x3fe8bf3c,0xbf553641,0x3f5bfb34,0xbf02ef9f,0x3f4cae79,0xbf19c200,0x3f3b0629,0xbf2ecef7,
0x3f800000,0x0,0x3f7e2b72,0xbdf475c0,0x3f78b47b,0xbe72b651,0x3f6faf1b,0xbeb3dca5,0x3fe33c5a,0xbf6bcbbb,0x3f5389c7,0xbf102dd5,0x3f40d0da,0xbf286605,0x3f2b561b,0xbf3e35c5,
0x3f800000,0x0,0x3f7dc68c,0xbe06b26e,0x3f772417,0xbe8586ce,0x3f6c3624,0xbec5625c,0x3fdd2d53,0xbf80e7e4,0x3f4a4c87,0xbf1ce11f,0x3f33e7bc,0xbf36206c,0x3f1a6293,0xbf4c3578,
0x3f800000,0x0,0x3f7d57de,0xbe1324ca,0x3f756d97,0xbe919ddd,0x3f686b39,0xbed6a399,0x3fd695e5,0xbf8b9a6b,0x3f404c5c,0xbf28fd41,0x3f26050a,0xbf42de29,0x3f084b92,0xbf58b3a1,
0x3f800000,0x0,0x3f7cdf6c,0xbe1f917b,0x3f73913f,0xbe9d9e78,0x3f644fac,0xbee79a5d,0x3fcf7a1f,0xbf95f6d9,0x3f3592e7,0xbf34768f,0x3f173c07,0xbf4e8d90,0x3eea6681,0xbf6398ac,
0x3f800000,0x0,0x3f7c5d3a,0xbe2bf804,0x3f718f57,0xbea986c4,0x3f5fe4e9,0xbef840c8,0x3fc7de65,0xbf9ff6cb,0x3f2a2a80,0xbf3f41fc,0x3f07a136,0xbf591e6a,0x3ec27b55,0xbf6cd007,
0x3f800000,0x0,0x3f7bd14d,0xbe3857ec,0x3f6f6830,0xbeb554ec,0x3f5b2c79,0xbf044889,0x3fbfc767,0xbfa99415,0x3f1e1e22,0xbf495521,0x3eee9479,0xbf628210,0x3e9920fe,0xbf74484b,
0x3f800000,0x0,0x3f7b3bab,0xbe44b0b9,0x3f6d1c1d,0xbec1071e,0x3f5627fe,0xbf0c42c9,0x3fb73a23,0xbfb2c8c9,0x3f11796b,0xbf52a649,0x3ecc9b8b,0xbf6aab7b,0x3e5d4b1a,0xbf79f35e,
0x3f800000,0x0,0x3f7a9c59,0xbe5101f1,0x3f6aab7b,0xbecc9b8b,0x3f50d937,0xbf140c5f,0x3fae3bde,0xbfbb8f3b,0x3f044889,0xbf5b2c79,0x3ea986c4,0xbf718f57,0x3e06b26e,0xbf7dc68c,
0x3f800000,0x0,0x3f79f35e,0xbe5d4b1a,0x3f6816a8,0xbed8106b,0x3f4b41fa,0xbf1ba299,0x3fa4d225,0xbfc3e200,0x3eed3063,0xbf62df7b,0x3e8586ce,0xbf772417,0x3d3c6dd5,0xbf7fba9e,
0x3f800000,0x0,0x3f7940c0,0xbe698bba,0x3f655e0b,0xbee363fa,0x3f456439,0xbf2302d3,0x3f9b02c6,0xbfcbbbf8,0x3ed0eb2a,0xbf69b7e4,0x3e419b37,0xbf7b61fc,0xbd2351cb,0xbf7fcbe2,
0x3f800000,0x0,0x3f788486,0xbe75c35a,0x3f628210,0xbeee9479,0x3f3f41fc,0xbf2a2a80,0x3f90d3cd,0xbfd31849,0x3eb3dca5,0xbf6faf1b,0x3dee3876,0xbf7e4323,0xbe007745,0xbf7dfa38,
0x3f800000,0x0,0x3f77beb7,0xbe80f8c0,0x3f5f8327,0xbef9a02d,0x3f38dd65,0xbf311722,0x3f864b82,0xbfd9f26a,0x3e9620d2,0xbf74bf62,0x3d2fe007,0xbf7fc38f,0xbe57278f,0xbf7a4910,
0x3f800000,0x0,0x3f76ef5b,0xbe870ada,0x3f5c61c7,0xbf0242b1,0x3f3238aa,0xbf37c655,0x3f76e0cb,0xbfe04621,0x3e6fa8b2,0xbf78e3d6,0xbcfb49ba,0xbf7fe129,0xbe9620d2,0xbf74bf62,
0x3f800000,0x0,0x3f76167a,0xbe8d17c0,0x3f591e6a,0xbf07a136,0x3f2b561b,0xbf3e35c5,0x3f60924f,0xbfe60f88,0x3e3228d4,0xbf7c187a,0xbdd53db9,0xbf7e9bc9,0xbebf926f,0xbf6d67a1,
0x3f800000,0x0,0x3f75341d,0xbe931f35,0x3f55b993,0xbf0cead0,0x3f24381a,0xbf446337,0x3f49b953,0xbfeb4b0c,0x3de7fa9a,0xbf7e5a38,0xbe354098,0xbf7bf531,0xbee79a5d,0xbf644fac,
0x3f800000,0x0,0x3f74484b,0xbe9920fe,0x3f5233c6,0xbf121eb0,0x3f1ce11f,0xbf4a4c87,0x3f3263ef,0xbfeff573,0x3d55880e,0xbf7fa6e3,0xbe7ee6e1,0xbf77f110,0xbf06f686,0xbf5988ad,
0x3f800000,0x0,0x3f73530e,0xbe9f1cdf,0x3f4e8d90,0xbf173c07,0x3f1553b7,0xbf4fefa8,0x3f1aa086,0xbff40bdd,0xbc16cb58,0xbf7ffd39,0xbea395c5,0xbf7294f8,0xbf19210f,0xbf4d26fd,
0x3f800000,0x0,0x3f725470,0xbea5129f,0x3f4ac77f,0xbf1c420c,0x3f0d9281,0xbf554aa4,0x3f027dc0,0xbff78bc5,0xbd9064b4,0xbf7f5ce9,0xbec6d529,0xbf6be858,0xbf2a2a80,0xbf3f41fc,
0x3f800000,0x0,0x3f714c7a,0xbeab0201,0x3f46e22a,0xbf212ff9,0x3f05a02c,0xbf5a5ba0,0x3ed41501,0xbffa7302,0xbe06b26e,0xbf7dc68c,0xbee900b7,0xbf63f473,0xbf39f2ac,0xbf2ff3e6,
0x3f800000,0x0,0x3f703b37,0xbeb0eacb,0x3f42de29,0xbf26050a,0x3efafef7,0xbf5f20db,0x3ea2abb6,0xbffcbfc9,0xbe44b0b9,0xbf7b3bab,0xbf04f484,0xbf5ac450,0xbf485bca,0xbf1f599f,
0x3f800000,0x0,0x3f6f20b0,0xbeb6ccc3,0x3f3ebc1b,0xbf2ac082,0x3eea6681,0xbf6398ac,0x3e61bc2e,0xbffe70b0,0xbe80f8c0,0xbf77beb7,0xbf14b039,0xbf5064af,0xbf554aa4,0xbf0d9281,
0x3f800000,0x0,0x3f6dfcf2,0xbebca7af,0x3f3a7ca4,0xbf2f61a5,0x3ed97cb9,0xbf67c187,0x3dfb2b74,0xbfff84ab,0xbe9f1cdf,0xbf73530e,0xbf239da9,0xbf44e3f5,0xbf60a6cf,0xbef58035,
0x3f800000,0x0,0x3f6cd007,0xbec27b55,0x3f36206c,0xbf33e7bc,0x3ec8477c,0xbf6b99fb,0x3cc90e90,0xbffffb11,0xbebca7af,0xbf6dfcf2,0xbf31a81d,0xbf385216,0xbf6a5ad9,0xbece0bea,
0x3f800000,0x0,0x0,0x0,0x0,0x0,0x0,0x0,0x0,0x0,0x0,0x0,0x0,0x0,0x0,0x0,
0x0,0x0,0x0,0x0,0x0,0x0,0x0,0x0,0x0,0x0,0x0,0x0,0x0,0x0,0x0,0x0,
0x0,0x0,0x3e000000,0xbf20dff7,0x3ed0c429,0x0,0x3e000000,0x3e61f78b,0x3e0a8bd4,0x0,0x3e000000,0x3d5413cd,0x3d5df9ad,0x0,0x3e000000,0x3cf043ab,
0x0,0x0,0x3e000000,0x3ccbafaf,0xbd5df9ad,0x0,0x3e000000,0x3cf043ab,0xbe0a8bd4,0x0,0x3e000000,0x3d5413cd,0xbed0c429,0x0,0x3e000000,0x3e61f78b,
0x0,0x0,0x0,0x0,0x3f000000,0x0,0x0,0x3f000000,0x0,0x0,0x0,0x0,0x0,0x0,0x0,0x0,
0x0,0x0,0x0,0x0,0x0,0x0,0x0,0x0,0x0,0x0,0x0,0x0,0x3f000000,0x0,0x0,0xbf000000,
0x0,0x0,0x3e000000,0xbe3f90c7,0xbe8b7e3f,0x0,0x3e000000,0xbeb641af,0x3ea73d75,0x0,0x3e000000,0x3e9a827a,0x3da61ad1,0x0,0x3e000000,0x3dd906bd,
0x0,0x0,0x3e000000,0x3dab0dc1,0xbda61ad1,0x0,0x3e000000,0x3dd906bd,0xbea73d75,0x0,0x3e000000,0x3e9a827a,0x3e8b7e3f,0x0,0x3e000000,0xbeb641af,
0x0,0x0,0x0,0x0,0x0,0x0,0x0,0x0,0x3f000000,0x0,0x0,0x3f000000,0x0,0x0,0x0,0x0,
0x0,0x0,0x0,0x0,0x0,0x0,0x0,0x0,0x3f000000,0x0,0x0,0xbf000000,0x0,0x0,0x0,0x0,
0x0,0x0,0x3e000000,0xbdab0dc1,0xbda61ad1,0x0,0x3e000000,0xbdd906bd,0xbea73d75,0x0,0x3e000000,0xbe9a827a,0x3e8b7e3f,0x0,0x3e000000,0x3eb641af,
0x0,0x0,0x3e000000,0x3e3f90c7,0xbe8b7e3f,0x0,0x3e000000,0x3eb641af,0x3ea73d75,0x0,0x3e000000,0xbe9a827a,0x3da61ad1,0x0,0x3e000000,0xbdd906bd,
0x0,0x0,0x0,0x0,0x0,0x0,0x0,0x0,0x0,0x0,0x0,0x0,0x3f000000,0x0,0x0,0x3f000000,
0x0,0x0,0x0,0x0,0x3f000000,0x0,0x0,0xbf000000,0x0,0x0,0x0,0x0,0x0,0x0,0x0,0x0,
0x0,0x0,0x3e000000,0xbccbafaf,0xbd5df9ad,0x0,0x3e000000,0xbcf043ab,0xbe0a8bd4,0x0,0x3e000000,0xbd5413cd,0xbed0c429,0x0,0x3e000000,0xbe61f78b,
0x0,0x0,0x3e000000,0x3f20dff7,0x3ed0c429,0x0,0x3e000000,0xbe61f78b,0x3e0a8bd4,0x0,0x3e000000,0xbd5413cd,0x3d5df9ad,0x0,0x3e000000,0xbcf043ab,
};

struct Params {
    const __nv_bfloat16 *wr, *wi, *lre, *lim, *ldt, *dsk;
    float* out;
};

struct cf { float x, y; };
#define YIELD() asm volatile("pmevent 1;")
#define YS 15
#define YIELD_S1() do { if (YS & 1) YIELD(); } while (0)
#define YIELD_S2() do { if (YS & 2) YIELD(); } while (0)
#define YIELD_S3() do { if (YS & 4) YIELD(); } while (0)
__device__ __forceinline__ uint32_t smem_u32(const void* p) { return (uint32_t)__cvta_generic_to_shared(p); }
__device__ __forceinline__ void mbar_init(uint32_t a, uint32_t c) { asm volatile("mbarrier.init.shared::cta.b64 [%0], %1;" ::"r"(a), "r"(c) : "memory"); }
__device__ __forceinline__ void mbar_expect_tx(uint32_t a, uint32_t b) { asm volatile("mbarrier.arrive.expect_tx.shared::cta.b64 _, [%0], %1;" ::"r"(a), "r"(b) : "memory"); }
__device__ __forceinline__ void mbar_arrive(uint32_t a) { asm volatile("mbarrier.arrive.shared::cta.b64 _, [%0];" ::"r"(a) : "memory"); }
__device__ __forceinline__ void warp_arrive(uint32_t a) {
    __syncwarp();
    asm volatile("{.reg .pred p; elect.sync _|p, 0xffffffff; @p mbarrier.arrive.shared::cta.b64 _, [%0];}" ::"r"(a) : "memory");
}
__device__ __forceinline__ uint32_t mbar_try(uint32_t a, uint32_t ph) {
    uint32_t ok;
    asm volatile("{.reg .pred p; mbarrier.try_wait.parity.shared::cta.b64 p, [%1], %2; selp.u32 %0, 1, 0, p;}" : "=r"(ok) : "r"(a), "r"(ph) : "memory");
    return ok;
}
__device__ __forceinline__ void mbar_wait(uint32_t a, uint32_t ph) {
    uint32_t ok, n = 0;
    do { ok = mbar_try(a, ph); } while (!ok && ++n < SPIN_LIMIT);
}
__device__ __forceinline__ void mbar_wait_fast(uint32_t a, uint32_t ph) { if (!mbar_try(a, ph)) mbar_wait(a, ph); }
__device__ __forceinline__ unsigned ld_rlx(const unsigned* p) { unsigned v; asm volatile("ld.relaxed.gpu.global.u32 %0, [%1];" : "=r"(v) : "l"(p) : "memory"); return v; }
__device__ __forceinline__ void wait_cnt(const unsigned* p, unsigned target) {
    unsigned n = 0;
    while ((int)(ld_rlx(p) - target) < 0 && ++n < SPIN_LIMIT) __nanosleep(20);
}
__device__ __forceinline__ void red_hint(unsigned* p) { asm volatile("red.relaxed.gpu.global.add.u32 [%0], 1;" ::"l"(p) : "memory"); }
__device__ __forceinline__ void fence_async() { asm volatile("fence.proxy.async.global;" ::: "memory"); }
__device__ __forceinline__ void fence_async_sm() { asm volatile("fence.proxy.async.shared::cta;" ::: "memory"); }
#define bar_sync(id, n) asm volatile("bar.sync %0, %1;" ::"n"(id), "n"(n) : "memory")
#define bar_arrive(id, n) asm volatile("bar.arrive %0, %1;" ::"n"(id), "n"(n) : "memory")
__device__ __forceinline__ bool elect_one() {
    uint32_t r;
    asm volatile("{.reg .pred p; elect.sync _|p, 0xffffffff; selp.u32 %0, 1, 0, p;}" : "=r"(r));
    return r != 0;
}

__device__ __forceinline__ void tma2d(uint32_t dst, const CUtensorMap* m, int c0, int c1, uint32_t bar) {
    asm volatile("cp.async.bulk.tensor.2d.shared::cluster.global.mbarrier::complete_tx::bytes [%0], [%1, {%3,%4}], [%2];" ::"r"(dst), "l"(m), "r"(bar), "r"(c0), "r"(c1) : "memory");
}
__device__ __forceinline__ void tma3d(uint32_t dst, const CUtensorMap* m, int c0, int c1, int c2, uint32_t bar) {
    asm volatile("cp.async.bulk.tensor.3d.shared::cluster.global.mbarrier::complete_tx::bytes [%0], [%1, {%3,%4,%5}], [%2];" ::"r"(dst), "l"(m), "r"(bar), "r"(c0), "r"(c1), "r"(c2) : "memory");
}
__device__ __forceinline__ void tma2d_mc(uint32_t dst, const CUtensorMap* m, int c0, int c1, uint32_t bar) {
    asm volatile("cp.async.bulk.tensor.2d.shared::cluster.global.mbarrier::complete_tx::bytes.multicast::cluster [%0], [%1, {%3,%4}], [%2], %5;" ::"r"(dst), "l"(m), "r"(bar), "r"(c0), "r"(c1), "h"((uint16_t)3) : "memory");
}
__device__ __forceinline__ void tma4d_mc(uint32_t dst, const CUtensorMap* m, int c0, int c1, int c2, int c3, uint32_t bar) {
    asm volatile("cp.async.bulk.tensor.4d.shared::cluster.global.mbarrier::complete_tx::bytes.multicast::cluster [%0], [%1, {%3,%4,%5,%6}], [%2], %7;" ::"r"(dst), "l"(m), "r"(bar), "r"(c0), "r"(c1), "r"(c2), "r"(c3), "h"((uint16_t)3) : "memory");
}
__device__ __forceinline__ void tma4d(uint32_t dst, const CUtensorMap* m, int c0, int c1, int c2, int c3, uint32_t bar) {
    asm volatile("cp.async.bulk.tensor.4d.shared::cluster.global.mbarrier::complete_tx::bytes [%0], [%1, {%3,%4,%5,%6}], [%2];" ::"r"(dst), "l"(m), "r"(bar), "r"(c0), "r"(c1), "r"(c2), "r"(c3) : "memory");
}
__device__ __forceinline__ void tma2d_st(const CUtensorMap* m, int c0, int c1, uint32_t src) {
    asm volatile("cp.async.bulk.tensor.2d.global.shared::cta.bulk_group [%0, {%2,%3}], [%1];" ::"l"(m), "r"(src), "r"(c0), "r"(c1) : "memory");
}
__device__ __forceinline__ void tma3d_st(const CUtensorMap* m, int c0, int c1, int c2, uint32_t src) {
    asm volatile("cp.async.bulk.tensor.3d.global.shared::cta.bulk_group [%0, {%2,%3,%4}], [%1];" ::"l"(m), "r"(src), "r"(c0), "r"(c1), "r"(c2) : "memory");
}
__device__ __forceinline__ void tma5d(uint32_t dst, const CUtensorMap* m, int c0, int c1, int c2, int c3, int c4, uint32_t bar) {
    asm volatile("cp.async.bulk.tensor.5d.shared::cluster.global.mbarrier::complete_tx::bytes [%0], [%1, {%3,%4,%5,%6,%7}], [%2];" ::"r"(dst), "l"(m), "r"(bar), "r"(c0), "r"(c1), "r"(c2), "r"(c3), "r"(c4) : "memory");
}
__device__ __forceinline__ void tma5d_mc(uint32_t dst, const CUtensorMap* m, int c0, int c1, int c2, int c3, int c4, uint32_t bar) {
    asm volatile("cp.async.bulk.tensor.5d.shared::cluster.global.mbarrier::complete_tx::bytes.multicast::cluster [%0], [%1, {%3,%4,%5,%6,%7}], [%2], %8;" ::"r"(dst), "l"(m), "r"(bar), "r"(c0), "r"(c1), "r"(c2), "r"(c3), "r"(c4), "h"((uint16_t)3) : "memory");
}
__device__ __forceinline__ void bulk_pf(const void* src, uint32_t n) { asm volatile("cp.async.bulk.prefetch.L2.global [%0], %1;" ::"l"(src), "r"(n) : "memory"); }
__device__ __forceinline__ void tma4d_pf(const CUtensorMap* m, int c0, int c1, int c2, int c3) {
    asm volatile("cp.async.bulk.prefetch.tensor.4d.L2.global [%0, {%1,%2,%3,%4}];" ::"l"(m), "r"(c0), "r"(c1), "r"(c2), "r"(c3) : "memory");
}
__device__ __forceinline__ void tma5d_pf(const CUtensorMap* m, int c0, int c1, int c2, int c3, int c4) {
    asm volatile("cp.async.bulk.prefetch.tensor.5d.L2.global [%0, {%1,%2,%3,%4,%5}];" ::"l"(m), "r"(c0), "r"(c1), "r"(c2), "r"(c3), "r"(c4) : "memory");
}
__device__ __forceinline__ void bulk_ld(uint32_t dst, const void* src, uint32_t n, uint32_t bar) {
    asm volatile("cp.async.bulk.shared::cluster.global.mbarrier::complete_tx::bytes [%0], [%1], %2, [%3];" ::"r"(dst), "l"(src), "r"(n), "r"(bar) : "memory");
}
__device__ __forceinline__ void bulk_st(void* dst, uint32_t src, uint32_t n) {
    asm volatile("cp.async.bulk.global.shared::cta.bulk_group [%0], [%1], %2;" ::"l"(dst), "r"(src), "r"(n) : "memory");
}
__device__ __forceinline__ void bulk_commit() { asm volatile("cp.async.bulk.commit_group;" ::: "memory"); }
__device__ __forceinline__ void bulk_wait_read() { asm volatile("cp.async.bulk.wait_group.read 0;" ::: "memory"); }
__device__ __forceinline__ void bulk_wait_all() { asm volatile("cp.async.bulk.wait_group 0;" ::: "memory"); }
__device__ __forceinline__ void stsm4(uint32_t a, uint32_t r0, uint32_t r1, uint32_t r2, uint32_t r3) {
    asm volatile("stmatrix.sync.aligned.m8n8.x4.shared.b16 [%0], {%1,%2,%3,%4};" ::"r"(a), "r"(r0), "r"(r1), "r"(r2), "r"(r3) : "memory");
}
__device__ __forceinline__ void sts128(uint32_t a, uint32_t r0, uint32_t r1, uint32_t r2, uint32_t r3) {
    asm volatile("st.shared.v4.b32 [%0], {%1,%2,%3,%4};" ::"r"(a), "r"(r0), "r"(r1), "r"(r2), "r"(r3) : "memory");
}
__device__ __forceinline__ void lds128f(uint32_t a, float& x, float& y, float& z, float& u) { asm volatile("ld.shared.v4.f32 {%0,%1,%2,%3}, [%4];" : "=f"(x), "=f"(y), "=f"(z), "=f"(u) : "r"(a) : "memory"); }
__device__ __forceinline__ cf lds_cf(uint32_t a) { cf v; asm volatile("ld.shared.v2.f32 {%0,%1}, [%2];" : "=f"(v.x), "=f"(v.y) : "r"(a) : "memory"); return v; }
__device__ __forceinline__ void stg128(const void* a, uint32_t r0, uint32_t r1, uint32_t r2, uint32_t r3) {
    asm volatile("st.global.v4.b32 [%0], {%1,%2,%3,%4};" ::"l"(a), "r"(r0), "r"(r1), "r"(r2), "r"(r3) : "memory");
}
__device__ __forceinline__ int fresh_lane() { int v; asm volatile("mov.u32 %0, %%laneid;" : "=r"(v)); return v; }
__device__ __forceinline__ uint32_t opaque32(uint32_t v) { asm volatile("" : "+r"(v)); return v; }
__device__ __forceinline__ const uint8_t* padd(const void* base, uint32_t off) {
    uint64_t r;
    asm("{.reg .u32 l, h; mov.b64 {l, h}, %1; add.cc.u32 l, l, %2; addc.u32 h, h, 0; mov.b64 %0, {l, h};}" : "=l"(r) : "l"(base), "r"(off));
    return (const uint8_t*)r;
}
template <int N, int STRIDE> __device__ __forceinline__ void ldtab(uint32_t (&v)[4 * N], uint32_t off) {
    const uint8_t* a = padd(g_tab, off);
#pragma unroll
    for (int i = 0; i < N; i++)
        asm volatile("ld.global.nc.v4.b32 {%0,%1,%2,%3}, [%4];" : "=r"(v[4 * i]), "=r"(v[4 * i + 1]), "=r"(v[4 * i + 2]), "=r"(v[4 * i + 3]) : "l"(a + i * STRIDE));
}
template <int STRIDE> __device__ __forceinline__ void ldtab_cf(cf (&t)[8], uint32_t off) {
    uint32_t v[16];
    ldtab<4, STRIDE>(v, off);
#pragma unroll
    for (int i = 0; i < 8; i++) t[i] = {__uint_as_float(v[2 * i]), __uint_as_float(v[2 * i + 1])};
}
__device__ __forceinline__ uint32_t lds16(uint32_t a) { uint32_t v; asm volatile("ld.shared.u16 %0, [%1];" : "=r"(v) : "r"(a)); return v; }
__device__ __forceinline__ unsigned get_epoch(uint32_t bars) {
    mbar_wait(bars + B_EP, 0);
    unsigned e;
    asm volatile("ld.shared.u32 %0, [%1];" : "=r"(e) : "r"(bars + B_EPOCH) : "memory");
    return e;
}
__device__ __forceinline__ void sts64(uint32_t a, uint32_t x, uint32_t y) { asm volatile("st.shared.v2.b32 [%0], {%1,%2};" ::"r"(a), "r"(x), "r"(y) : "memory"); }
__device__ __forceinline__ uint32_t pk(float lo, float hi) { uint32_t r; asm("cvt.rn.bf16x2.f32 %0, %1, %2;" : "=r"(r) : "f"(hi), "f"(lo)); return r; }
__device__ __forceinline__ float bf2f(unsigned short v) { return __uint_as_float((uint32_t)v << 16); }

__device__ __forceinline__ uint64_t mkdesc(uint32_t addr, uint32_t lbo, uint32_t sbo, uint32_t swz) {
    return (uint64_t)((addr & 0x3FFFF) >> 4) | ((uint64_t)(lbo >> 4) << 16) | ((uint64_t)(sbo >> 4) << 32) | ((uint64_t)swz << 62);
}
__device__ __forceinline__ uint64_t opaque(uint64_t v) { asm volatile("" : "+l"(v)); return v; }
__device__ __forceinline__ void wg_fence() { asm volatile("wgmma.fence.sync.aligned;" ::: "memory"); }
__device__ __forceinline__ void wg_commit() { asm volatile("wgmma.commit_group.sync.aligned;" ::: "memory"); }
template <int N> __device__ __forceinline__ void wg_wait() { asm volatile("wgmma.wait_group.sync.aligned %0;" ::"n"(N) : "memory"); }
template <int N> __device__ __forceinline__ void pin(float (&d)[N]) {
#pragma unroll
    for (int i = 0; i < N; i++) asm volatile("" : "+f"(d[i])::"memory");
}
template <int N> __device__ __forceinline__ void pinu(uint32_t (&d)[N]) {
#pragma unroll
    for (int i = 0; i < N; i++) asm volatile("" : "+r"(d[i])::"memory");
}

#define R8(d, o) "+f"(d[o]), "+f"(d[o + 1]), "+f"(d[o + 2]), "+f"(d[o + 3]), "+f"(d[o + 4]), "+f"(d[o + 5]), "+f"(d[o + 6]), "+f"(d[o + 7])
#define L8 "%0,%1,%2,%3,%4,%5,%6,%7"
#define L32 L8 ",%8,%9,%10,%11,%12,%13,%14,%15,%16,%17,%18,%19,%20,%21,%22,%23,%24,%25,%26,%27,%28,%29,%30,%31"
#define L56 L32 ",%32,%33,%34,%35,%36,%37,%38,%39,%40,%41,%42,%43,%44,%45,%46,%47,%48,%49,%50,%51,%52,%53,%54,%55"
#define L64 L56 ",%56,%57,%58,%59,%60,%61,%62,%63"

template <int O, int TA, int TB, int N> __device__ __forceinline__ void mma128_ss(float (&d)[N], uint64_t da, uint64_t db, int sc) {
    asm volatile("{.reg .pred p; setp.ne.b32 p, %66, 0;\n"
                 "wgmma.mma_async.sync.aligned.m64n128k16.f32.bf16.bf16 {" L64 "}, %64, %65, p, 1, 1, %67, %68;}"
                 : R8(d, O), R8(d, O + 8), R8(d, O + 16), R8(d, O + 24), R8(d, O + 32), R8(d, O + 40), R8(d, O + 48), R8(d, O + 56)
                 : "l"(da), "l"(db), "r"(sc), "n"(TA), "n"(TB));
}
template <int O, int TB> __device__ __forceinline__ void mma128_rs(float (&d)[128], uint32_t a0, uint32_t a1, uint32_t a2, uint32_t a3, uint64_t db, int sc) {
    asm volatile("{.reg .pred p; setp.ne.b32 p, %69, 0;\n"
                 "wgmma.mma_async.sync.aligned.m64n128k16.f32.bf16.bf16 {" L64 "}, {%64,%65,%66,%67}, %68, p, 1, 1, %70;}"
                 : R8(d, O), R8(d, O + 8), R8(d, O + 16), R8(d, O + 24), R8(d, O + 32), R8(d, O + 40), R8(d, O + 48), R8(d, O + 56)
                 : "r"(a0), "r"(a1), "r"(a2), "r"(a3), "l"(db), "r"(sc), "n"(TB));
}
template <int TB> __device__ __forceinline__ void mma64_rs(float (&d)[32], uint32_t a0, uint32_t a1, uint32_t a2, uint32_t a3, uint64_t db, int sc) {
    asm volatile("{.reg .pred p; setp.ne.b32 p, %37, 0;\n"
                 "wgmma.mma_async.sync.aligned.m64n64k16.f32.bf16.bf16 {" L32 "}, {%32,%33,%34,%35}, %36, p, 1, 1, %38;}"
                 : R8(d, 0), R8(d, 8), R8(d, 16), R8(d, 24)
                 : "r"(a0), "r"(a1), "r"(a2), "r"(a3), "l"(db), "r"(sc), "n"(TB));
}
__device__ __forceinline__ void mma112_ss(float (&d)[64], uint64_t da, uint64_t db, int sc) {
    asm volatile("{.reg .pred p; setp.ne.b32 p, %58, 0;\n"
                 "wgmma.mma_async.sync.aligned.m64n112k16.f32.bf16.bf16 {" L56 "}, %56, %57, p, 1, 1, 0, 1;}"
                 : R8(d, 8), R8(d, 16), R8(d, 24), R8(d, 32), R8(d, 40), R8(d, 48), R8(d, 56)
                 : "l"(da), "l"(db), "r"(sc));
}
__device__ __forceinline__ void mma16_rs(float (&d)[64], uint32_t a0, uint32_t a1, uint32_t a2, uint32_t a3, uint64_t db, int sc) {
    asm volatile("{.reg .pred p; setp.ne.b32 p, %13, 0;\n"
                 "wgmma.mma_async.sync.aligned.m64n16k16.f32.bf16.bf16 {" L8 "}, {%8,%9,%10,%11}, %12, p, 1, 1, 1;}"
                 : R8(d, 0)
                 : "r"(a0), "r"(a1), "r"(a2), "r"(a3), "l"(db), "r"(sc));
}

__device__ __forceinline__ cf cmul(cf a, cf b) { return {fmaf(a.x, b.x, -a.y * b.y), fmaf(a.x, b.y, a.y * b.x)}; }
__device__ __forceinline__ cf cmulc(cf a, cf b) { return {fmaf(a.x, b.x, a.y * b.y), fmaf(a.y, b.x, -a.x * b.y)}; }
__device__ __forceinline__ cf cfma(cf a, cf b, cf c) { return {fmaf(a.x, b.x, fmaf(-a.y, b.y, c.x)), fmaf(a.x, b.y, fmaf(a.y, b.x, c.y))}; }
__device__ __forceinline__ cf csq(cf a) { return {fmaf(a.x, a.x, -a.y * a.y), (a.x * a.y) * 2.f}; }
__device__ __forceinline__ cf csel(int c, cf a, cf b) {
    cf r;
    asm("{.reg .pred p; setp.ne.s32 p, %2, 0; selp.f32 %0, %3, %5, p; selp.f32 %1, %4, %6, p;}" : "=f"(r.x), "=f"(r.y) : "r"(c), "f"(a.x), "f"(a.y), "f"(b.x), "f"(b.y));
    return r;
}
__device__ __forceinline__ cf cadd(cf a, cf b) { return {a.x + b.x, a.y + b.y}; }
__device__ __forceinline__ cf csub(cf a, cf b) { return {a.x - b.x, a.y - b.y}; }
__device__ __forceinline__ cf twice_minus(cf a, cf s) { return {fmaf(2.f, a.x, -s.x), fmaf(2.f, a.y, -s.y)}; }
__device__ __forceinline__ cf twid(int m, int M) {
    int r = ((m + M / 2) & (M - 1)) - M / 2;
    float s, c;
    __sincosf((float)r * (-6.283185307179586f / (float)M), &s, &c);
    return {c, s};
}
struct c2 { cf a, b; };
#define YF 1
__device__ __forceinline__ void fin(c2& u) { if (YF) asm volatile("pmevent 1;" : "+f"(u.a.x), "+f"(u.a.y), "+f"(u.b.x), "+f"(u.b.y)); }
__device__ __forceinline__ void fin(c2& u, c2& v) {
    if (YF) asm volatile("pmevent 1;" : "+f"(u.a.x), "+f"(u.a.y), "+f"(u.b.x), "+f"(u.b.y), "+f"(v.a.x), "+f"(v.a.y), "+f"(v.b.x), "+f"(v.b.y));
}
__device__ __forceinline__ c2 mul2(c2 u, cf t) { return {cmul(u.a, t), cmul(u.b, t)}; }
__device__ __forceinline__ c2 mul2(c2 u, c2 t) { return {cmul(u.a, t.a), cmul(u.b, t.b)}; }
__device__ __forceinline__ c2 fma2(c2 u, cf t, c2 c) { return {cfma(u.a, t, c.a), cfma(u.b, t, c.b)}; }
__device__ __forceinline__ c2 fma2(c2 u, c2 t, c2 c) { return {cfma(u.a, t.a, c.a), cfma(u.b, t.b, c.b)}; }
__device__ __forceinline__ c2 twm2(c2 u, c2 s) { return {twice_minus(u.a, s.a), twice_minus(u.b, s.b)}; }
__device__ __forceinline__ void bfly(c2& u, c2& v) { const c2 t = u; u = {cadd(t.a, v.a), cadd(t.b, v.b)}; v = {csub(t.a, v.a), csub(t.b, v.b)}; fin(u, v); }
__device__ __forceinline__ void bfly_mi(c2& u, c2& v) {
    const c2 t = u, z = v;
    u = {{t.a.x + z.a.y, t.a.y - z.a.x}, {t.b.x + z.b.y, t.b.y - z.b.x}};
    v = {{t.a.x - z.a.y, t.a.y + z.a.x}, {t.b.x - z.b.y, t.b.y + z.b.x}};
    fin(u, v);
}
__device__ __forceinline__ void bfly_s(c2& u, c2& v) {
    const float s = 0.70710678118654752f;
    const c2 t = u, z = v;
    u = {{fmaf(s, z.a.x, t.a.x), fmaf(s, z.a.y, t.a.y)}, {fmaf(s, z.b.x, t.b.x), fmaf(s, z.b.y, t.b.y)}};
    v = {{fmaf(-s, z.a.x, t.a.x), fmaf(-s, z.a.y, t.a.y)}, {fmaf(-s, z.b.x, t.b.x), fmaf(-s, z.b.y, t.b.y)}};
    fin(u, v);
}
template <class T> __device__ __forceinline__ void bfly_tw(c2& u0, c2& v0, T t0, c2& u1, c2& v1, T t1) {
    v0 = fma2(v0, t0, u0); fin(v0);
    v1 = fma2(v1, t1, u1); fin(v1);
    const c2 a = twm2(u0, v0), b = twm2(u1, v1);
    u0 = v0; u1 = v1; v0 = a; v1 = b;
    fin(v0, v1);
}
template <bool TW> __device__ __forceinline__ void dft8(c2 (&v)[8], const cf (&tw)[8]) {
    if (TW) {
#pragma unroll
        for (int n = 1; n < 4; n++) { v[n] = mul2(v[n], tw[n]); fin(v[n]); }
        bfly_tw(v[0], v[4], tw[4], v[2], v[6], tw[6]);
        bfly_tw(v[1], v[5], tw[5], v[3], v[7], tw[7]);
    } else {
#pragma unroll
        for (int n = 0; n < 4; n++) bfly(v[n], v[n + 4]);
    }
    bfly(v[0], v[2]); bfly_mi(v[4], v[6]);
    bfly(v[1], v[3]); bfly_mi(v[5], v[7]);
    v[5] = {{v[5].a.x + v[5].a.y, v[5].a.y - v[5].a.x}, {v[5].b.x + v[5].b.y, v[5].b.y - v[5].b.x}};
    v[7] = {{v[7].a.y - v[7].a.x, -v[7].a.x - v[7].a.y}, {v[7].b.y - v[7].b.x, -v[7].b.x - v[7].b.y}};
    fin(v[5], v[7]);
    bfly(v[0], v[1]); bfly_s(v[4], v[5]); bfly_mi(v[2], v[3]); bfly_s(v[6], v[7]);
    const c2 t1 = v[1], t3 = v[3];
    v[1] = v[4]; v[4] = t1; v[3] = v[6]; v[6] = t3;
}

__device__ __forceinline__ void gather(uint32_t (&fv)[8], const uint8_t* a, int n, uint32_t tag) {
    asm volatile("{.reg .pred p0, p1, p2, p3; .reg .b64 a0, a1, a2, a3;\n"
                 "setp.ge.s32 p0, %9, 0; setp.ge.s32 p1, %9, 4; setp.ge.s32 p2, %9, 8; setp.ge.s32 p3, %9, 12;\n"
                 "mov.b64 a0, {%10,%10}; mov.b64 a1, a0; mov.b64 a2, a0; mov.b64 a3, a0;\n"
                 "@p0 ld.relaxed.gpu.global.b64 a0, [%8]; @p1 ld.relaxed.gpu.global.b64 a1, [%8+-32768];\n"
                 "@p2 ld.relaxed.gpu.global.b64 a2, [%8+-65536]; @p3 ld.relaxed.gpu.global.b64 a3, [%8+-98304];\n"
                 "mov.b64 {%0,%1}, a0; mov.b64 {%2,%3}, a1; mov.b64 {%4,%5}, a2; mov.b64 {%6,%7}, a3;}"
                 : "=r"(fv[0]), "=r"(fv[1]), "=r"(fv[2]), "=r"(fv[3]), "=r"(fv[4]), "=r"(fv[5]), "=r"(fv[6]), "=r"(fv[7]) : "l"(a), "r"(n), "r"(tag) : "memory");
}
template <int H> __device__ __forceinline__ void prescale(float (&u)[64], const float (&d)[128], cf gam) {
#pragma unroll
    for (int i = 0; i < 32; i += 2) {
        const int r = 2 * i + 2 * H;
        c2 v = mul2(c2{{d[r], -d[64 + r]}, {d[r + 1], -d[65 + r]}}, gam);
        if (YS & 2) asm volatile("pmevent 1;" : "+f"(v.a.x), "+f"(v.a.y), "+f"(v.b.x), "+f"(v.b.y));
        u[i] = v.a.x; u[32 + i] = v.a.y; u[i + 1] = v.b.x; u[33 + i] = v.b.y;
    }
}
__device__ __forceinline__ void scan2(const float (&u)[64], cf lam, cf st, const uint8_t* hptr, uint32_t hm, uint32_t hb, uint32_t& keep) {
    uint32_t hp[32];
#pragma unroll
    for (int jj = 0; jj < 4; jj++) {
        cf v[8];
#pragma unroll
        for (int i = 0; i < 8; i++) v[i] = st = cfma(lam, st, {u[8 * jj + i], u[32 + 8 * jj + i]});
        const int o = 8 * jj;
        hp[o] = pk(v[0].x, v[2].x); hp[o + 1] = pk(v[4].x, v[6].x); hp[o + 2] = pk(v[1].x, v[3].x); hp[o + 3] = pk(v[5].x, v[7].x);
        hp[o + 4] = pk(v[0].y, v[2].y); hp[o + 5] = pk(v[4].y, v[6].y); hp[o + 6] = pk(v[1].y, v[3].y); hp[o + 7] = pk(v[5].y, v[7].y);
        hp[o + jj] = (hp[o + jj] & hm) | hb;
        hp[o + 4 + jj] = (hp[o + 4 + jj] & hm) | hb;
        stg128(hptr + (jj >> 1) * 8192 + (jj & 1) * 512, hp[o], hp[o + 1], hp[o + 2], hp[o + 3]);
        stg128(hptr + 16384 + (jj >> 1) * 8192 + (jj & 1) * 512, hp[o + 4], hp[o + 5], hp[o + 6], hp[o + 7]);
        YIELD_S3();
        if (jj > 0) {
#pragma unroll
            for (int i = o - 8; i < o; i += 2) asm volatile("lop3.b32 %0, %0, %1, %2, 0x80;" : "+r"(keep) : "r"(hp[i]), "r"(hp[i + 1]));
        }
    }
}

__device__ __forceinline__ int pos_of(int n) { return (n & 24) + 4 * (n & 1) + ((n >> 1) & 3); }
__device__ __forceinline__ int unit_of(int role, int u, int& slot) {
    const int g = role & 7, w = (role >> 3) & 3, b = role >> 5;
    slot = role >= 128 ? g : (g ? 16 * g + w + 4 * b : 4 * w + b);
    return role >= 128 ? 32 * max(2 * g + u, 1) : (g ? g + 16 * w : ((w & 1) << 4) + ((w & 2) << 2)) + 64 * b + 256 * u;
}
template <int STRIDE> __device__ __forceinline__ bool tags_ok(uint32_t a, uint32_t ep) {
    uint32_t v[4], ok;
#pragma unroll
    for (int i = 0; i < 4; i++) asm volatile("ld.shared.u32 %0, [%1];" : "=r"(v[i]) : "r"(a + i * STRIDE) : "memory");
    asm volatile("{.reg .pred p; .reg .b32 a, b; lop3.b32 a, %1, %2, %5, 0x7e; lop3.b32 b, %3, %4, %5, 0x7e; lop3.b32 a, a, b, 1, 0xa8;\n"
                 "setp.eq.u32 p, a, 0; vote.sync.all.pred p, p, -1; selp.u32 %0, 1, 0, p;}" : "=r"(ok) : "r"(v[0]), "r"(v[1]), "r"(v[2]), "r"(v[3]), "r"(ep));
    return ok;
}
__device__ __forceinline__ void load_w_rows(uint32_t dst, const CUtensorMap* mr, const CUtensorMap* mi, int kap, uint32_t bar) {
    mbar_expect_tx(bar, 16 * WPITCH);
#pragma unroll 1
    for (int i = 0; i < 2; i++, dst += 8 * WPITCH, kap = (512 - kap) & 511) {
        tma2d(dst, mr, (kap * 1026 >> 4) * 2, 0, bar);
        tma2d(dst + 4 * WPITCH, mi, (kap * 1026 >> 4) * 2, 0, bar);
    }
}
__device__ __forceinline__ void prefetch_w_rows(const CUtensorMap* mr, const CUtensorMap* mi, int kap) {
#pragma unroll 1
    for (int i = 0; i < 2; i++, kap = (512 - kap) & 511) {
        asm volatile("cp.async.bulk.prefetch.tensor.2d.L2.global [%0, {%1,%2}];" ::"l"(mr), "r"((kap * 1026 >> 4) * 2), "r"(0) : "memory");
        asm volatile("cp.async.bulk.prefetch.tensor.2d.L2.global [%0, {%1,%2}];" ::"l"(mi), "r"((kap * 1026 >> 4) * 2), "r"(0) : "memory");
    }
}
#define SB0 1024
__device__ __forceinline__ uint64_t ring_desc(uint32_t sb, uint32_t off, uint32_t lbo, uint32_t swz) {
    uint64_t d;
    asm volatile("{.reg .b32 z; shr.u32 z, %1, 28; mov.b64 %0, {z, z}; add.u64 %0, %0, %2;}" : "=l"(d) : "r"(sb), "l"(mkdesc(SB0 + off, lbo, 1024, swz)));
    return d;
}
struct Ring {
    uint32_t full, rel;
    uint32_t n;
    bool sig;
};
__device__ __forceinline__ void ring_release(const Ring& r, uint32_t o) {
    if (r.sig) asm volatile("mbarrier.arrive.shared::cluster.b64 _, [%0];" ::"r"(r.rel + o) : "memory");
}
__device__ __forceinline__ void peek(uint32_t a, uint32_t ph) { asm volatile("mbarrier.test_wait.parity.shared::cta.b64 pk, [%0], %1;" ::"r"(a), "r"(ph) : "memory"); }
__device__ __forceinline__ void peek_wait(uint32_t a, uint32_t ph, uint32_t& n) {
    asm volatile("{@pk bra DONE;\n"
                 "LOOP: mbarrier.try_wait.parity.shared::cta.b64 pk, [%1], %2; add.u32 %0, %0, 1; setp.gt.or.u32 pk, %0, %3, pk; @!pk bra LOOP;\n"
                 "DONE: }" : "+r"(n) : "r"(a), "r"(ph), "n"(SPIN_LIMIT) : "memory");
}
#define SL(k) ((k) % NST)
#define PH(k) (((k) / NST) & 1)
#define HANDPOS 5
#define H64 "%64,%65,%66,%67,%68,%69,%70,%71,%72,%73,%74,%75,%76,%77,%78,%79,%80,%81,%82,%83,%84,%85,%86,%87,%88,%89,%90,%91,%92,%93,%94,%95," \
            "%96,%97,%98,%99,%100,%101,%102,%103,%104,%105,%106,%107,%108,%109,%110,%111,%112,%113,%114,%115,%116,%117,%118,%119,%120,%121,%122,%123,%124,%125,%126,%127"
#define WG_MMA "wgmma.mma_async.sync.aligned.m64n128k16.f32.bf16.bf16 "
#define DESC_B(S, j) "mov.b64 {t, hb}, %130; mov.b64 db, {%137 + 2048 * " #S " + 2 * " #j ", hb};\n"
#define MMA_LO(S, j, p) "add.u64 da, %129, 2048 * " #S " + %136 * " #j ";" DESC_B(S, j) WG_MMA "{" L64 "}, da, db, " #p ", 1, 1, %138, 0;\n"
#define MMA_HI(S, j, p) "add.u64 da, %129, 2048 * " #S " + 512 + %136 * " #j ";\n" WG_MMA "{" H64 "}, da, db, " #p ", 1, 1, %138, 0;\n"
#define STEP(S, P, N, ph, pa, pr, X, Y) \
    "wgmma.fence.sync.aligned;\n" MMA_LO(S, 0, pa) MMA_HI(S, 0, pa) \
    "wgmma.commit_group.sync.aligned; wgmma.wait_group.sync.aligned 1; @" #pr " mbarrier.arrive.shared::cluster.b64 _, [%132 + 8 * " #P "];\n" MMA_LO(S, 1, 1) \
    "mbarrier.test_wait.parity.shared::cta.b64 pk, [%131 + 8 * " #N "], " #ph ";\n" MMA_HI(S, 1, 1) MMA_LO(S, 2, 1) X MMA_HI(S, 2, 1) MMA_LO(S, 3, 1) MMA_HI(S, 3, 1) \
    "wgmma.commit_group.sync.aligned;\n" P4A Y "@pk bra GO" #S ";\n" \
    "WAIT" #S ": mbarrier.try_wait.parity.shared::cta.b64 pk, [%131 + 8 * " #N "], " #ph "; add.u32 %128, %128, 1; setp.gt.or.u32 pk, %128, %139, pk; @!pk bra WAIT" #S ";\n" \
    "GO" #S ":\n" P4B
#define P4A
#define P4B
#define P4I
#define P4O
#define STEP_ARGS(TA) \
    : R8(d, 0), R8(d, 8), R8(d, 16), R8(d, 24), R8(d, 32), R8(d, 40), R8(d, 48), R8(d, 56), \
      R8(d, 64), R8(d, 72), R8(d, 80), R8(d, 88), R8(d, 96), R8(d, 104), R8(d, 112), R8(d, 120), "+r"(r.n) \
    : "l"(ha), "l"(hb), "r"(r.full), "r"(r.rel), "r"((uint32_t)r.sig), "r"(wg), \
      "n"(SB0 / 16 + (TA ? 32 << 16 : 1 << 16)), "n"(TA ? 128 : 2), "n"(SB0 / 16 + 1024 + (1 << 16)), "n"(TA), "n"(SPIN_LIMIT) P4O \
    : "memory"
#define STEP_REGS "{.reg .b32 k, t, ph, hb; .reg .b64 da, db; .reg .pred ps, pl, pa, pr;\n" P4I "setp.ne.u32 ps, %133, 0;\n"
__device__ __forceinline__ void gemm1(float (&d)[128], Ring& r, uint64_t ha, uint64_t hb, int wg) {
    asm volatile(STEP_REGS "mul.lo.u32 k, %134, 15; mov.b32 ph, %134; setp.ne.u32 pl, k, 0; @pl bra ONE;\n"
                 "LOOP: setp.ne.u32 pa, k, 0; and.pred pr, pa, ps; setp.eq.u32 pl, k, 15;\n"
                 STEP(0, 4, 1, ph, pa, pr, "@pl bar.arrive 1, 256;\n", "@pl bra END;\n")
                 "ONE: setp.ne.u32 pa, k, 15; and.pred pr, pa, ps; setp.eq.u32 pl, k, 30;\n"
                 STEP(1, 0, 2, ph, pa, pr, "@pl bar.arrive 2, 256;\n", "@pl bra END;\n")
                 STEP(2, 1, 3, ph, 1, ps, "", "") STEP(3, 2, 4, ph, 1, ps, "", "") "xor.b32 ph, ph, 1; add.u32 k, k, 5;\n" STEP(4, 3, 0, ph, 1, ps, "", "")
                 "bra LOOP;\n"
                 "END:\n" P4B "}" STEP_ARGS(0));
}
__device__ __forceinline__ void gemm2(float (&d)[128], Ring& r, uint64_t ha, uint64_t hb, int wg) {
    asm volatile(STEP_REGS "mov.b32 k, 0; mov.b32 ph, 0;\n"
                 "LOOP: setp.ne.u32 pa, k, 0; and.pred pr, pa, ps; setp.eq.u32 pl, k, 5;\n"
                 STEP(2, 1, 3, ph, pa, pr, "", "") STEP(3, 2, 4, ph, 1, ps, "", "") "xor.b32 ph, ph, 1; add.u32 k, k, 1;\n" STEP(4, 3, 0, ph, 1, ps, "", "")
                 "@pl bra END;\n" STEP(0, 4, 1, ph, 1, ps, "", "") STEP(1, 0, 2, ph, 1, ps, "", "")
                 "bra LOOP;\n"
                 "END: }" STEP_ARGS(1));
}
template <int O, int K, int J> __device__ __forceinline__ void mma_h(float (&y)[128], uint64_t a, uint64_t b) { mma128_ss<O, 1, 0>(y, a + SL(K) * 2048 + O * 8 + 128 * J, b + SL(K) * 2048 + 2 * J, 1); }
template <int O, int K> __device__ __forceinline__ void half_step(float (&y)[128], uint64_t a, uint64_t b) { mma_h<O, K, 0>(y, a, b); mma_h<O, K, 1>(y, a, b); mma_h<O, K, 2>(y, a, b); mma_h<O, K, 3>(y, a, b); }
template <int R, int U> __device__ __forceinline__ void out_piece(float (&y)[128], const uint32_t (&dd)[16], uint32_t x0, uint32_t x1, float* op) {
    const int i = 64 * (R >> 1) + 8 * U + 2 * (R & 1);
    asm("mul.rn.bf16x2 %0, %0, %1;" : "+r"(x0) : "r"(dd[2 * U]));
    asm("mul.rn.bf16x2 %0, %0, %1;" : "+r"(x1) : "r"(dd[2 * U + 1]));
    asm volatile("st.global.v4.f32 [%0], {%1,%2,%3,%4};" ::"l"(op + (32 * (R & 1) + 16 * (R >> 1)) * 2048 + 16 * U),
                 "f"(y[i] + __uint_as_float(x0 << 16)), "f"(y[i + 1] + __uint_as_float(x0 & 0xffff0000u)),
                 "f"(y[i + 4] + __uint_as_float(x1 << 16)), "f"(y[i + 5] + __uint_as_float(x1 & 0xffff0000u)) : "memory");
}
template <int R, int U0> __device__ __forceinline__ void load_x4(uint32_t (&xx)[8], uint32_t xa) {
#pragma unroll
    for (int u = 0; u < 4; u++)
        asm volatile("ld.shared.v2.b32 {%0,%1}, [%2];" : "=r"(xx[2 * u]), "=r"(xx[2 * u + 1]) : "r"((xa ^ (u << 5)) + (3 - R) * 8192 + U0 * 1024) : "memory");
}
__device__ __forceinline__ Ring ring_at(uint32_t sb, int k) {
    Ring r;
    r.n = 0;
    r.full = sb + OFF_BAR + B_FULL;
    asm("mapa.shared::cluster.u32 %0, %1, %2;" : "=r"(r.rel) : "r"(sb + OFF_BAR + B_EMPTY), "r"((threadIdx.x >> 5) & 1));
    r.sig = __shfl_sync(~0u, threadIdx.x & 95, threadIdx.x) == 0;
    return r;
}

template <bool BY_SM> __global__ void __cluster_dims__(2, 1, 1) __launch_bounds__(512, 1)
fused_kernel(const __grid_constant__ CUtensorMap tmX, const __grid_constant__ CUtensorMap tmBre, const __grid_constant__ CUtensorMap tmBim,
             const __grid_constant__ CUtensorMap tmCre, const __grid_constant__ CUtensorMap tmCim, const __grid_constant__ CUtensorMap tmXd,
             const __grid_constant__ CUtensorMap tmUst, const __grid_constant__ CUtensorMap tmVst,
             const __grid_constant__ CUtensorMap tmWr, const __grid_constant__ CUtensorMap tmWi, const __grid_constant__ CUtensorMap tmXa,
             const Params p) {
    extern __shared__ __align__(1024) uint8_t smraw[];
    asm volatile(".reg .pred pk, p0;");
    const int tid = threadIdx.x, rank = blockIdx.x & 1;
    const uint32_t wi = __shfl_sync(~0u, smem_u32(smraw) + (tid >> 5), 0), sb = wi & ~15u, bars = sb + OFF_BAR;
    const int wg = (wi >> 2) & 3, w = wi & 3, lane = tid & 31, g = lane >> 2, q = lane & 3;
    if (wg != 3) asm volatile("barrier.cluster.arrive.relaxed.aligned; barrier.cluster.wait.aligned;" ::: "memory");
    else asm volatile("prefetch.tensormap [%0];" ::"l"(w == 0 ? &tmX : w == 1 ? &tmBre : &tmBim) : "memory");
    int role;
    {
        uint32_t T = blockIdx.x;
        if (BY_SM) asm("mov.u32 %0, %%smid;" : "=r"(T));
        T >>= 1;
        const uint32_t a = ((T - 32) * 37) >> 8;
        asm("{.reg .pred p; setp.lt.u32 p, %1, 62; selp.u32 %0, 4, -58, p; add.u32 %0, %0, %1;\n"
            "setp.lt.u32 p, %1, 60; selp.u32 %0, %2, %0, p; setp.lt.u32 p, %1, 32; selp.u32 %0, %3, %0, p;}"
            : "=&r"(role) : "r"(T), "r"(8 * (T - 31 - 7 * a) + 4 + a), "r"(8 * (T & 7) + (T >> 3)));
        role = 2 * role + rank;
    }
    const bool spare = role >= 128;
    const int tc = ((role >> 3) & 14) + rank, cb = (role >> 1) & 7;
    const int fb = role >> 5, fcb = role & 31, fpos = pos_of(fcb);
    const int nu = role == 128 ? 1 : (fcb || !role ? 2 : 0);

    if (wg == 3) {
        if (elect_one()) {
            const uint32_t b = bars + w * 8;
            STAMP5(57);
            mbar_init(b, 1);
            if (w < 2 && !spare) {
                mbar_expect_tx(b, 32768);
                tma5d(sb + w * 32768 + 16384, &tmX, w * 64, 0, 0, 0, tc, b);
                if (w == 0) { tma4d(sb, &tmBre, 0, 0, 0, cb * 4, b); tma4d(sb + 8192, &tmBim, 0, 0, 0, cb * 4, b); }
                STAMP5(58);
            }
#pragma unroll
            for (int o = 32; o < B_EPOCH; o += 32) mbar_init(b + o, o < B_EMPTY ? 1 : (o < B_STG ? 2 : (o < B_P3M ? 4 : 8)));
            asm volatile("fence.mbarrier_init.release.cluster;" ::: "memory");
        }
        __syncwarp();
        STAMP5(59);
        asm volatile("barrier.cluster.arrive.relaxed.aligned;" ::: "memory");
    }
    if (opaque32(wg) == 3) {
        asm volatile("setmaxnreg.dec.sync.aligned.u32 24;");
        asm volatile("barrier.cluster.wait.aligned;" ::: "memory");
        if (w == 0) {
            if (!spare && elect_one()) {
                int s = 0, ph = 0;
                STAMP(56);
#pragma unroll 1
                for (int k = 1; k < NST; k++) {
                    if (k >= 2) mbar_expect_tx(bars + B_FULL + k * 8, 32768);
                    tma4d_mc(sb + k * 32768 + rank * 8192, rank ? &tmBim : &tmBre, k * 64, 0, 0, cb * 4, bars + B_FULL + k * 8);
                    if (k >= 2) tma5d(sb + k * 32768 + 16384, &tmX, k * 64, 0, 0, 0, tc, bars + B_FULL + k * 8);
                }
#pragma unroll 1
                for (int k = NST; k < 64; k++) {
                    const uint32_t fbar = bars + B_FULL + s * 8, a = sb + s * 32768;
                    mbar_wait(bars + B_EMPTY + s * 8, ph);
                    if (k < 32) {
                        const int kk = (k & 15) * 64;
                        mbar_expect_tx(fbar, 32768);
                        tma4d_mc(a + rank * 8192, rank ? &tmBim : &tmBre, kk, 0, (k >> 4) * 2, cb * 4, fbar);
                        tma5d(a + 16384, &tmX, kk, 0, 0, 0, tc, fbar);
                    } else {
                        const int kk = k - 32;
                        asm volatile("mbarrier.expect_tx.shared::cta.b64 [%0], 16384;" ::"r"(fbar) : "memory");
                        tma5d_mc(a + 16384 + rank * 8192, (kk & 1) ? &tmCim : &tmCre, (kk >> 1) * 64, 0, 0, 0, cb * 8 + rank * 4, fbar);
                        if ((kk & 7) == 0) { mbar_wait(bars + B_HOWN + kk, 0); STAMPO(45, (kk >> 3)); }
                        mbar_expect_tx(bars + B_HL + s * 16 + (kk & 1) * 8, 16384);
                        bulk_ld(a, g_H + (size_t)(tc * 32 + kk) * 16384, 16384, bars + B_HL + s * 16 + (kk & 1) * 8);
                    }
                    if (k == 10 + (tc & 14)) tma4d_pf(rank ? &tmBim : &tmBre, (tc & 14) * 64, 0, 2, cb * 4);
                    if (k == 26 + (tc & 14) * 2) {
                        tma5d_pf(rank ? &tmCim : &tmCre, (tc & 14) * 64, 0, 0, 0, cb * 8);
                        tma5d_pf(rank ? &tmCim : &tmCre, (tc & 14) * 64, 0, 0, 0, cb * 8 + 4);
                    }
                    if (++s == NST) { s = 0; ph ^= 1; }
                }
            }
        } else if (opaque32(w) == 1) {
            const unsigned ep = ld_rlx(g_epoch + role * 8) + 1;
            __syncwarp();
            if (elect_one()) {
                asm volatile("st.relaxed.gpu.global.u32 [%0], %1;" ::"l"(g_epoch + role * 8), "r"(ep) : "memory");
                asm volatile("st.shared.u32 [%0], %1;" ::"r"(bars + B_EPOCH), "r"(ep) : "memory");
                mbar_arrive(bars + B_EP);
            }
            int slot;
            const int kap = unit_of(role, 0, slot), kap1 = unit_of(role, 1, slot);
            uint32_t lph = 0;
#pragma unroll 1
            for (int e = 0; e < 4; e++) {
                if (e < 2) {
                    if (!spare) mbar_wait(bars + B_STGU, 0);
                    if (!e) STAMP(21);
                } else {
                    if (e - 2 < nu) mbar_wait(bars + B_WFREE, e & 1);
                    if (e == 2) {
                        if (nu == 2 && elect_one()) load_w_rows(sb + OFF_WD, &tmWr, &tmWi, kap1, bars + B_WD);
                    } else if (!spare) {
                        mbar_wait(bars + B_HOWN + 8, 0);
#pragma unroll 1
                        for (int r = 0; r < 3; r++) {
                            if (elect_one()) {
                                if (r == 0) { mbar_expect_tx(bars + B_XD, 24576 + 256); bulk_ld(sb + OFF_LAM, p.dsk + cb * 128, 256, bars + B_XD); }
                                tma4d(sb + OFF_F + (3 - r) * 8192, &tmXd, 0, tc * 128 + 32 * (r & 1) + 16 * (r >> 1), 0, cb * 2, bars + B_XD);
                            }
                            __nanosleep(PACE_X);
                        }
                    }
                    if (e - 2 < nu) mbar_wait(bars + B_STG, e & 1);
                    STAMPO(23, e - 2);
                }
                if (elect_one()) {
                    if (e < 2 ? !spare : (e - 2 < nu && role + e != 2)) {
                        const uint32_t src = sb + OFF_P + (role || e < 2 ? (e & 1) * 16384 : 0);
                        const int c0 = e < 2 ? fb * 2048 + fpos * 64 : ((e & 1) * 256 + slot) * 32;
                        if (e == 0) {
#pragma unroll 1
                            for (int r = 4; r < 8; r++) bulk_st(g_X + r * (32 * 16384) + c0 * 2, src + r * 4096, 128);
                        }
                        tma2d_st(e < 2 ? &tmUst : &tmVst, c0, e < 2 ? e * 128 : 0, src);
                        bulk_commit();
                        tma2d_st(e < 2 ? &tmUst : &tmVst, e < 2 ? c0 : c0 + 4096, e < 2 ? e * 128 + 64 : 0, src + 8192);
                        bulk_commit();
                        asm volatile("cp.async.bulk.wait_group.read 1;" ::: "memory");
                        red_hint(g_cnt + e * 32);
                    }
                    if (e == 0 || (e == 3 && !spare)) {
                        mbar_expect_tx(bars + B_FG, 8192);
                        bulk_ld(sb + OFF_F, (const uint8_t*)g_tab + (e ? TAB_G + fb * 8192 : TAB_FG), 8192, bars + B_FG);
                    }
                    bulk_wait_read();
                }
                STAMPO(28, e == 0 ? 12 : (e == 3 ? 15 : 0));
                const uint32_t tg = e < 2 ? lane * 128 + ((((lane >> 1) & 2) ^ (lane & 3)) << 4) + (lane >> 3) * 4 : lane * 64 + (lane & 8) * 4 + (lane & 2) * 8 + (lane & 4) * 2;
                if (spare) {
                    if (e == 1) {
                        wait_cnt(g_cnt, 128 * ep);
                        STAMP(42);
#pragma unroll 1
                        for (int n = 0; n < 4096; n++) {
                            if (elect_one()) {
                                mbar_expect_tx(bars + B_LD, 8 * 16384);
#pragma unroll 1
                                for (int r = 0; r < 8; r++) bulk_ld(sb + r * 16384, g_X + (size_t)r * (32 * 16384), 16384, bars + B_LD);
                            }
                            mbar_wait(bars + B_LD, n & 1);
                            bool ok = true;
#pragma unroll 1
                            for (int r = 0; r < 8; r++) ok &= tags_ok<4096>(sb + r * 16384 + tg, ep);
                            if (ok) break;
                        }
                        if (elect_one()) mbar_arrive(bars + B_RAW);
                    }
                } else if (e < 2 ? nu != 0 : role + e != 2) {
#pragma unroll 1
                    for (int x = role || e < 3 ? e : 2; x <= e; x++) {
                        const uint32_t dst = sb + OFF_P + (x & 1) * 16384;
                        wait_cnt(g_cnt + x * 32, 128 * ep);
                        STAMPO(41, x == 2 ? -12 : x);
#pragma unroll 1
                        for (int n = 0; n < 4096; n++) {
                            if (elect_one()) { mbar_expect_tx(bars + B_LD, 16384); bulk_ld(dst, g_X + (size_t)(e < 2 ? role + e * 128 : 254 + (fb * 32 + fpos) * 2 + x) * 16384, 16384, bars + B_LD); }
                            mbar_wait(bars + B_LD, lph);
                            if (!e) STAMP3(49);
                            lph ^= 1;
                            if (tags_ok<4096>(dst + tg, ep) & tags_ok<4096>(dst + tg + (e & 2) * 1024, ep)) break;
                        }
                        if (role == 0 && e < 2) {
#pragma unroll 1
                            for (int i = 0; i < 16; i++) sts128(dst + i * 1024 + g * 128 + 64 + q * 16, 0, 0, 0, 0);
                            fence_async_sm();
                        }
                        if (elect_one()) mbar_arrive(bars + B_IN + x * 8);
                    }
                }
                if (e < 2 && nu && elect_one()) {
                    if (e) prefetch_w_rows(&tmWr, &tmWi, kap1);
                    else load_w_rows(sb + OFF_WD, &tmWr, &tmWi, kap, bars + B_WD);
                }
            }
            if (!spare) {
                mbar_wait(bars + B_P3M, 0);
                if (elect_one()) { mbar_expect_tx(bars + B_XD + 8, 8192); tma4d(sb + OFF_F, &tmXd, 0, tc * 128 + 48, 0, cb * 2, bars + B_XD + 8); }
            }
        } else {
            if (w == 2) {
                {
                    const int u = lane >> 4;
                    int slot;
                    const int r0 = unit_of(role, u, slot) + 512 * ((lane >> 1) & 3), r1 = (2048 - r0) & 2047, mir = (lane >> 3) & 1;
                    const unsigned short* wp = (const unsigned short*)((lane & 1) ? p.wi : p.wr);
                    const float a = bf2f(wp[r0 * 513 + mir * 512]), b = bf2f(wp[r1 * 513 + mir * 512]);
                    asm volatile("st.shared.f32 [%0], %1;" ::"r"(sb + OFF_WSP + u * 64 + (lane & 15) * 4), "f"(0.5f * ((lane & 1) ? (mir ? b - a : a - b) : a + b)) : "memory");
                }
                warp_arrive(bars + B_WSP);
            } else if (!spare) {
                if (XA_T0) __nanosleep(XA_T0);
#pragma unroll 1
                for (int i = 0; i < 8; i++) {
                    if (i >= XA_N0) __nanosleep(XA_PACE);
                    if (elect_one()) {
                        if (i == 0) mbar_expect_tx(bars + B_XIN, 32768);
                        tma3d(sb + OFF_F + i * 4096, &tmXa, fcb * 32, 0, 4 * i + fb, bars + B_XIN);
                    }
                }
            }
            if (!spare) {
                if (w == 2 && nu) {
                    mbar_wait(bars + B_STGU, 0);
                    int slot;
                    const int kap = unit_of(role, 0, slot);
                    if (elect_one()) prefetch_w_rows(&tmWr, &tmWi, kap);
                }
                const unsigned ep = get_epoch(bars);
                const uint32_t ca = sb + (q >> 1) * 8192 + (q & 1) * 512 + g * 1040 + q * 4, rb = bars + B_HR - 16 + w * 8;
                uint32_t rph = 0, hph = 0;
                int s = 32 % NST + w - 2, i5 = 0;
#pragma unroll 1
                for (int kk = w - 2; kk < 32; kk += 2) {
                    mbar_wait(bars + B_HL - 16 + s * 16 + w * 8, hph);
#pragma unroll 1
                    for (int n = 0; n < 4096; n++) {
                        if (tags_ok<128>(ca + s * 32768, ep)) break;
                        int k2 = kk;
                        asm volatile("" : "+r"(k2));
                        if (elect_one()) { mbar_expect_tx(rb, 16384); bulk_ld(sb + s * 32768, g_H + (size_t)(tc * 32 + k2) * 16384, 16384, rb); }
                        mbar_wait(rb, rph);
                        rph ^= 1;
                    }
                    if (elect_one()) mbar_arrive(bars + B_FULL + s * 8);
                    s += 2;
                    if (s >= NST) s -= NST;
                    if (++i5 == NST) { i5 = 0; hph ^= 1; }
                }
                if (w == 3) warp_arrive(bars + B_DONE);
            }
        }
    } else {
        STAMP(55);
        asm volatile("setmaxnreg.inc.sync.aligned.u32 152;");
        STAMP5(60);
        const int t7 = tid & 127, hf = wg - 1;
        const int mi = lane >> 3, gl = lane & 7;
        if (spare && wg != 2) {
            if (tid < 64) { const uint4 v = __ldg((const uint4*)((const uint8_t*)g_tab + TAB_PC) + tid); sts128(sb + OFF_LAM + tid * 16, v.x, v.y, v.z, v.w); }
            bar_sync(1, 256);
            mbar_wait(bars + B_RAW, 0);
            STAMP(0);
#pragma unroll 1
            for (int u = 0; u < nu; u++) {
                int slot;
                const int t = unit_of(role, u, slot) >> 5;
                const uint32_t off = (tid >> 2) * 128 + q * 16;
                float zr[16], zi[16];
#pragma unroll
                for (int k = 0; k < 16; k++) zr[k] = zi[k] = 0.f;
#pragma unroll 1
                for (int r = (t & 1) ? 0 : t >> 1; r < 8 - ((t & 1) ? 0 : (t >> 1) - 1); r += (t & 1) ? 1 : 8 - t) {
                    float4 c;
                    float a[8], b[8];
                    lds128f(sb + OFF_LAM + t * 128 + r * 16, c.x, c.y, c.z, c.w);
                    lds128f(sb + r * 16384 + off, a[0], a[1], a[2], a[3]);
                    lds128f(sb + r * 16384 + off + 64, b[0], b[1], b[2], b[3]);
                    lds128f(sb + r * 16384 + off + 8192, a[4], a[5], a[6], a[7]);
                    lds128f(sb + r * 16384 + off + 8192 + 64, b[4], b[5], b[6], b[7]);
#pragma unroll
                    for (int k = 0; k < 16; k++) {
                        const uint32_t ua = __float_as_uint(a[k >> 1]), ub = __float_as_uint(b[k >> 1]);
                        const float x = __uint_as_float((k & 1) ? ua & 0xffff0000u : ua << 16), y = __uint_as_float((k & 1) ? ub & 0xffff0000u : ub << 16);
                        zr[k] = fmaf(c.x, x, fmaf(c.z, y, zr[k]));
                        zi[k] = fmaf(c.y, x, fmaf(c.w, y, zi[k]));
                    }
                }
                const uint32_t dst = sb + OFF_P + u * 16384 + off;
#pragma unroll
                for (int k = 0; k < 16; k += 8) {
                    sts128(dst + k * 1024, pk(zr[k], zr[k + 1]), pk(zr[k + 2], zr[k + 3]), pk(zr[k + 4], zr[k + 5]), pk(zr[k + 6], zr[k + 7]));
                    sts128(dst + k * 1024 + 64, pk(zi[k], zi[k + 1]), pk(zi[k + 2], zi[k + 3]), pk(zi[k + 4], zi[k + 5]), pk(zi[k + 6], zi[k + 7]));
                }
                fence_async_sm();
                bar_sync(1, 256);
                if (tid == 0) mbar_arrive(bars + B_IN + u * 8);
                STAMPO(1, u);
            }
            return;
        }
        if (wg == 2 && !spare) {
            asm volatile("setmaxnreg.inc.sync.aligned.u32 176;");
            uint32_t f1[16];
            cf tw[8];
            if (TAB_T0) __nanosleep(TAB_T0);
            ldtab<4, 2048>(f1, TAB_F1 + t7 * 16);
            ldtab_cf<16>(tw, TAB_TW1 + (t7 >> 2) * 64);
            const uint32_t ep = get_epoch(bars);
            uint32_t a0 = sb + OFF_P + (8 * w + gl + 32 * (mi >> 1)) * 128 + (((((mi & 1) << 2) | (fpos & 3)) ^ gl) << 4);
            float acc[128];
            const uint64_t dx = opaque(mkdesc(sb + OFF_F, 4096, 512, 2));
            mbar_wait(bars + B_XIN, 0);
            STAMP(20);
            pinu(f1);
            wg_fence();
#pragma unroll
            for (int j = 0; j < 4; j++) {
                mma128_rs<0, 1>(acc, f1[4 * j], f1[4 * j + 1], f1[4 * j + 2], f1[4 * j + 3], dx + j * 64, j);
                mma128_rs<64, 1>(acc, f1[4 * j], f1[4 * j + 1], f1[4 * j + 2], f1[4 * j + 3], dx + 1024 + j * 64, j);
            }
            wg_commit();
            wg_wait<0>();
            pin(acc);
            pinu(f1);
#pragma unroll 1
            for (int h = 0;; h++) {
                const uint32_t tmask = 2 * q + h == fpos >> 2 ? ~1u : ~0u, tbit = ep & ~tmask;
#pragma unroll
                for (int cl = 0; cl < 2; cl++) {
                    c2 v[8];
#pragma unroll
                    for (int n = 0; n < 8; n++) {
                        const int i = 4 * (4 * n + cl);
                        v[n] = {{acc[i], acc[i + 2]}, {acc[i + 1], acc[i + 3]}};
                    }
                    dft8<true>(v, tw);
#pragma unroll
                    for (int r = 0; r < 8; r += 2) {
                        uint32_t o0 = pk(v[r].a.x, v[r].b.x), o1 = pk(v[r].a.y, v[r].b.y), o2 = pk(v[r + 1].a.x, v[r + 1].b.x), o3 = pk(v[r + 1].a.y, v[r + 1].b.y);
                        if (cl == 0) { o0 = (o0 & tmask) | tbit; o2 = (o2 & tmask) | tbit; }
                        stsm4((a0 ^ (cl << 4)) + r * 4096, o0, o1, o2, o3);
                    }
                }
                if (h) break;
                a0 ^= 32;
#pragma unroll
                for (int n = 0; n < 8; n++) {
                    asm volatile("mov.b32 %0, %8; mov.b32 %1, %9; mov.b32 %2, %10; mov.b32 %3, %11; mov.b32 %4, %12; mov.b32 %5, %13; mov.b32 %6, %14; mov.b32 %7, %15; pmevent 1;"
                                 : "=&f"(acc[16 * n]), "=&f"(acc[16 * n + 1]), "=&f"(acc[16 * n + 2]), "=&f"(acc[16 * n + 3]), "=&f"(acc[16 * n + 4]), "=&f"(acc[16 * n + 5]), "=&f"(acc[16 * n + 6]), "=&f"(acc[16 * n + 7])
                                 : "f"(acc[16 * n + 8]), "f"(acc[16 * n + 9]), "f"(acc[16 * n + 10]), "f"(acc[16 * n + 11]), "f"(acc[16 * n + 12]), "f"(acc[16 * n + 13]), "f"(acc[16 * n + 14]), "f"(acc[16 * n + 15]));
                }
            }
            fence_async_sm();
            warp_arrive(bars + B_STGU);
            bar_sync(3, 128);
            asm volatile("setmaxnreg.dec.sync.aligned.u32 152;");
            bar_arrive(7, 256);
        }
        if (wg == 1) {
            if (LAM_T0) __nanosleep(LAM_T0);
            const int cl = tid & 127, ch = (cl >> 6) * 512 + ((cl >> 3) & 1) * 256 + cb * 32 + ((cl >> 4) & 3) * 8 + (cl & 7);
            const float lr = bf2f(*(const unsigned short*)padd(p.lre, 2 * ch)), li = bf2f(*(const unsigned short*)padd(p.lim, 2 * ch));
            const float dt = __bfloat162float(__float2bfloat16(expf(bf2f(*(const unsigned short*)padd(p.ldt, 2 * ch)))));
            const float an = dt * li, th = an * 0.318309873342514f;
            float sn, cs, inv;
            sincospif(fmaf(rintf(0.5f * th), -2.f, th) + fmaf(an, 1.2841276653e-8f, fmaf(an, 0.318309873342514f, -th)), &sn, &cs);
            const float ex = expf(dt * lr), br = ex * cs, bi = ex * sn;
            asm("rcp.approx.f32 %0, %1;" : "=f"(inv) : "f"(lr * lr + li * li));
            inv += inv;
            const float cr = ((br - 1.f) * lr + bi * li) * inv, ci = (bi * lr - (br - 1.f) * li) * inv;
            sts128(sb + OFF_LAM + cl * 16, __float_as_uint(br), __float_as_uint(-bi), __float_as_uint(cr), __float_as_uint(-ci));
            mbar_wait(bars + B_EP, 0);
            bar_sync(8, 128);
            if (tid == 128) mbar_arrive(bars + B_LAM);
        }
        if (wg != 2) {
        if (wg == 0) bar_sync(4, 128); else bar_sync(7, 256);
        asm volatile("setmaxnreg.inc.sync.aligned.u32 160;");
        if (wg == 0) bar_sync(4, 128);
        float d[128];
        if (wg == 1) bar_sync(1, 256);
        STAMPW(0, 10);
        Ring rg = ring_at(sb, role * 66 + wg * 16);
        cf lam[2];
        unsigned ep;
        const uint32_t lama = sb + OFF_LAM + wg * 1024 + (16 * w + g) * 16;
        mbar_wait_fast(rg.full + 8 * wg, wg);
        gemm1(d, rg, ring_desc(sb, 0, 16, 1), ring_desc(sb, 16384, 16, 1), wg);
        mbar_wait_fast(bars + B_LAM, 0);
        lam[0] = lds_cf(lama); lam[1] = lds_cf(lama + 128);
        asm volatile("ld.shared.u32 %0, [%1];" : "=r"(ep) : "r"(bars + B_EPOCH) : "memory");
        asm volatile("setmaxnreg.inc.sync.aligned.u32 176;");
        cf L[2] = {lam[0], lam[1]};
#pragma unroll
        for (int i = 0; i < 4; i++) { L[0] = csq(L[0]); L[1] = csq(L[1]); }
        asm volatile("" : "+f"(L[0].x), "+f"(L[0].y), "+f"(L[1].x), "+f"(L[1].y)::"memory");
        wg_wait<0>();
        ring_release(rg, 8 * wg);
        pin(d);
        STAMPW(1, 11);
        {
            const int lane = fresh_lane(), g = lane >> 2, q = lane & 3, mi = lane >> 3, gl = lane & 7;
            cf f[2], fb2[2];
#pragma unroll
            for (int i = 0; i < 17; i++) {
#pragma unroll
                for (int h = 0; h < 2; h++) {
                    const int r = 4 * (i >> 1) + 2 * h + (i & 1), r2 = 32 + 4 * ((i - 1) >> 1) + 2 * h + ((i - 1) & 1);
                    if (i < 16) f[h] = i ? cfma(lam[h], f[h], {d[r], -d[64 + r]}) : cf{d[r], -d[64 + r]};
                    if (i > 0) fb2[h] = i > 1 ? cfma(lam[h], fb2[h], {d[r2], -d[64 + r2]}) : cf{d[r2], -d[64 + r2]};
                    if (i && (h || !(YS & 8))) YIELD_S1();
                }
            }
            const uint8_t* cbase = (const uint8_t*)g_carry + (tc * 16 + wg * 8 + cb) * 512 + w * 64;
            const uint8_t* cptr = padd(cbase, g * 8);
            const unsigned tag = ep & 15u;
#pragma unroll
            for (int h = 0; h < 2; h++) { f[h] = cfma(L[h], f[h], fb2[h]); L[h] = csq(L[h]); }
            cf s0[2], s1[2], s2[2];
#pragma unroll
            for (int h = 0; h < 2; h++) {
                s0[h] = {__shfl_sync(~0u, f[h].x, 0, 4), __shfl_sync(~0u, f[h].y, 0, 4)};
                s1[h] = {__shfl_sync(~0u, f[h].x, 1, 4), __shfl_sync(~0u, f[h].y, 1, 4)};
                s2[h] = {__shfl_sync(~0u, f[h].x, 2, 4), __shfl_sync(~0u, f[h].y, 2, 4)};
            }
#pragma unroll
            for (int h = 0; h < 2; h++) {
                s1[h] = cfma(L[h], s0[h], s1[h]);
                s2[h] = cfma(L[h], s1[h], s2[h]);
                f[h] = cfma(L[h], s2[h], f[h]);
                asm volatile("{.reg .pred p; .reg .b64 a; setp.eq.u32 p, %3, 3; mov.b64 a, {%1,%2}; @p st.relaxed.gpu.global.b64 [%0], a;}" ::"l"(cptr + h * 256),
                             "r"((__float_as_uint(f[h].x) & ~15u) | tag), "f"(f[h].y), "r"(q) : "memory");
            }
            STAMPX(2, 12);
            cf gam = lds_cf(lama + 8);
            cf st = csel(q & 2, csel(q & 1, s2[0], s1[0]), csel(q & 1, s0[0], {0.f, 0.f}));
            const cf st1 = csel(q & 2, csel(q & 1, s2[1], s1[1]), csel(q & 1, s0[1], {0.f, 0.f}));
            cptr = padd(cbase - 4 * 8192, (3 - mi) * 8192 + gl * 8);
            const int nprev = tc - 1 - mi;
            const uint8_t* hptr = padd(g_H + (size_t)(tc * 32 + wg * 16 + (cb & 6)) * 16384 + ((cb & 1) * 4 + w) * 1024, g * 64 + ((q ^ (g >> 1)) << 4));
            const uint32_t hm = 4 * (g & 1) + (q ^ (g >> 1)) == (cb & 1) * 4 + w ? ~1u : ~0u;
            float u[64];
            uint32_t fv[8];
            prescale<0>(u, d, gam);
            gather(fv, cptr, nprev, tag);
#pragma unroll 1
            for (int h = 0;; h++) {
                const cf L2 = csq(L[0]), M = csq(L2);
                cf M4 = csq(csq(M));
                M4 = {__shfl_sync(~0u, M4.x, 4 * gl), __shfl_sync(~0u, M4.y, 4 * gl)};
                cf lq = cmul(gam, cmul(csel(q & 1, L[0], {1.f, 0.f}), csel(q & 2, L2, {1.f, 0.f})));
                st = cmul(gam, st);
                asm volatile("pmevent 1;" : "+f"(lq.x), "+f"(lq.y), "+f"(st.x), "+f"(st.y));
#pragma unroll 1
                for (unsigned n = 0; __any_sync(~0u, ((fv[0] ^ tag) | (fv[2] ^ tag) | (fv[4] ^ tag) | (fv[6] ^ tag)) & 15u) && n < SPIN_LIMIT; n++) gather(fv, cptr, nprev, tag);
                if (!h) STAMPX(53, 54);
                cf P = {__uint_as_float(fv[6]), __uint_as_float(fv[7])}, pj[4];
#pragma unroll
                for (int a = 2; a >= 0; a--) P = cfma(M4, P, {__uint_as_float(fv[2 * a]), __uint_as_float(fv[2 * a + 1])});
                cptr += 256;
                gather(fv, cptr, h ? -1 : nprev, tag);
#pragma unroll
                for (int j = 3; j >= 0; j--) pj[j] = {__shfl_sync(~0u, P.x, g + 8 * j), __shfl_sync(~0u, P.y, g + 8 * j)};
                st = cfma(lq, cfma(M, cfma(M, cfma(M, pj[3], pj[2]), pj[1]), pj[0]), st);
                if (!h) STAMPX(3, 13);
                uint32_t keep = sb >> 28;
                scan2(u, lam[0], st, hptr, hm, ep & ~hm, keep);
                warp_arrive(bars + B_HOWN + wg * 16 + h * 8 + keep);
                if (h) break;
                STAMPW(4, 14);
                lds128f(lama + 128, lam[0].x, lam[0].y, gam.x, gam.y);
                st = st1;
                L[0] = L[1];
                hptr += 8 * 16384;
                prescale<1>(u, d, gam);
            }
            STAMPW(5, 15);
        }
        if (wg == 0) bar_sync(4, 128); else bar_sync(8, 128);
        if (wg == 0) {
            asm volatile("setmaxnreg.dec.sync.aligned.u32 160;");
            float y[128];
            rg = ring_at(sb, role * 66 + 32);
            STAMP(6);
            bar_sync(2, 256);
            STAMP(7);
            mbar_wait_fast(rg.full + SL(32) * 8, PH(32));
            const uint64_t dA = ring_desc(sb, 0, 512, 2), dB = ring_desc(sb, 16384, 16, 1);
            gemm2(y, rg, dA, dB, 0);
            asm volatile("setmaxnreg.inc.sync.aligned.u32 184;");
            const int lane = fresh_lane(), g = lane >> 2, q = lane & 3;
            const int pg = 2 * (g & 3) + (g >> 2);
            float* op = (float*)padd(p.out + (size_t)(tc * 128 + 64 * (w & 1) + 8 * (w >> 1)) * 2048 + 1024 + cb * 128, pg * 8192 + q * 16);
            const uint32_t xa = sb + OFF_F + (16 * (w & 1) + 8 * (w >> 1) + pg) * 128 + (((q >> 1) ^ pg) << 4) + (q & 1) * 8;
#define HALF0(k) wg_fence(); peek(k < 63 ? rg.full + SL(k + 1) * 8 : bars + B_XD, PH(k + 1)); half_step<0, k>(y, dA, dB); wg_commit(); peek_wait(k < 63 ? rg.full + SL(k + 1) * 8 : bars + B_XD, PH(k + 1), rg.n);
            HALF0(60) HALF0(61) HALF0(62) HALF0(63)
            const uint64_t dB2 = ring_desc(sb >> 1, 16384, 16, 1);
            uint32_t xa0[8], xa1[8], dd[16];
#pragma unroll
            for (int i = 0; i < 8; i++) asm volatile("ld.shared.v2.b32 {%0,%1}, [%2];" : "=r"(dd[2 * i]), "=r"(dd[2 * i + 1]) : "r"(sb + OFF_LAM + q * 8 + 32 * i) : "memory");
            load_x4<0, 0>(xa0, xa);
            wg_fence();
            half_step<64, 64 - SKEW>(y, dA, dB2);
            wg_commit();
            wg_wait<1>();
#pragma unroll
            for (int i = 0; i < 64; i++) asm volatile("" : "+f"(y[i])::"memory");
            STAMP(16);
#define MM(n) if (4 + (n) < 4 * SKEW) { wg_fence(); mma_h<64, 65 - SKEW + (n) / 4, (n) % 4>(y, dA, dB2); mma_h<64, 65 - SKEW + (n) / 4, (n) % 4 + 1>(y, dA, dB2); }
#define OUT4(R, U, X, n) out_piece<R, U>(y, dd, X[0], X[1], op); MM(n) out_piece<R, U + 1>(y, dd, X[2], X[3], op); MM(n + 2) \
                         out_piece<R, U + 2>(y, dd, X[4], X[5], op); MM(n + 4) out_piece<R, U + 3>(y, dd, X[6], X[7], op); MM(n + 6)
            load_x4<0, 4>(xa1, xa);
            OUT4(0, 0, xa0, 0)
            load_x4<1, 0>(xa0, xa);
            OUT4(0, 4, xa1, 8)
            wg_commit();
            load_x4<1, 4>(xa1, xa);
            OUT4(1, 0, xa0, 16)
            load_x4<2, 0>(xa0, xa);
            OUT4(1, 4, xa1, 16)
            STAMP(18);
            wg_wait<0>();
#pragma unroll
            for (int i = 64; i < 128; i++) asm volatile("" : "+f"(y[i])::"memory");
            STAMP(8);
            load_x4<2, 4>(xa1, xa);
            mbar_wait_fast(bars + B_XD + 8, 0);
            OUT4(2, 0, xa0, 16)
            load_x4<3, 0>(xa0, xa);
            OUT4(2, 4, xa1, 16)
            load_x4<3, 4>(xa1, xa);
            OUT4(3, 0, xa0, 16)
            OUT4(3, 4, xa1, 16)
            STAMP(9);
            return;
        }
        asm volatile("setmaxnreg.dec.sync.aligned.u32 152;");
        } else {
        if (nu) {
            cf T[8];
            ldtab_cf<2048>(T, TAB_T + t7 * 16);
            const uint32_t ep = get_epoch(bars);
            const int ka = pos_of(t7 >> 2);
            asm volatile("setp.eq.u32 p0, %0, 0;" ::"r"(__shfl_sync(~0u, t7, lane)));
            mbar_wait(bars + B_WSP, 0);
            mbar_wait(bars + B_FG, 0);
#pragma unroll 1
            for (int u = 0; u < nu; u++) {
                int slot;
                const int kap = unit_of(role, u, slot);
                const uint32_t buf = sb + OFF_P + u * 16384;
                float acc[64], za[32], zb[32], ya[32], yb[32], vv[64];
                const uint64_t dF = opaque(mkdesc(sb + OFF_F, 16, 1024, 1)), dB = opaque(mkdesc(buf, 4096, 512, 2));
                STAMP3(39);
                mbar_wait(bars + B_IN + u * 8, 0);
                STAMP3(22);
                wg_fence();
#pragma unroll
                for (int j = 0; j < 4; j++) mma128_ss<0, 0, 1>(acc, dF + j * 2, dB + j * 64, j);
                wg_commit();
                cf be1 = twid(kap + 512 * q, 2048), be2 = csq(be1), be3 = cmul(be1, be2);
                uint32_t wd[4], wm[4];
#pragma unroll
                for (int j = 0; j < 4; j++) {
                    wd[j] = sb + OFF_WD + ((j + q) & 3) * WPITCH + ((2 * kap) & 15) + 2 * ka + 64 * q;
                    wm[j] = sb + OFF_WM + (((kap ? 3 : 4) - j - q) & 3) * WPITCH + ((-2 * kap) & 15) + 1024 - 2 * ka - 64 * q;
                }
                asm volatile("" : "+f"(be1.x), "+f"(be1.y), "+f"(be2.x), "+f"(be2.y), "+f"(be3.x), "+f"(be3.y)::"memory");
                pinu(wd);
                pinu(wm);
                wg_wait<0>();
                pin(acc);
                STAMP3(30);
                uint32_t af[16], ag[16];
#pragma unroll
                for (int b = 0; b < 4; b++) {
                    uint32_t(&o)[16] = b < 2 ? af : ag;
#pragma unroll
                    for (int c = 0; c < 4; c++) {
                        const int i = 4 * (4 * b + c);
                        c2 x = mul2(c2{{acc[i], acc[i + 2]}, {acc[i + 1], acc[i + 3]}}, c2{T[2 * c], T[2 * c + 1]});
                        fin(x);
                        o[4 * c + (b & 1)] = pk(x.a.x, x.a.y);
                        o[4 * c + 2 + (b & 1)] = pk(x.b.x, x.b.y);
                    }
                    if (b & 1) {
                        pinu(o);
                        wg_fence();
#pragma unroll
                        for (int j = 0; j < 4; j++) mma64_rs<0>(b < 2 ? za : zb, o[4 * j], o[4 * j + 1], o[4 * j + 2], o[4 * j + 3], dF + j * 2, j);
                        wg_commit();
                    }
                }
                STAMP3(31);
                mbar_wait(bars + B_WD, u & 1);
                uint32_t wr[16];
#pragma unroll
                for (int i = 0; i < 16; i++) wr[i] = lds16(wd[i >> 2] + 256 * ((i >> 1) & 1) + (i & 1) * 4 * WPITCH);
                wg_wait<0>();
                pin(za);
                pin(zb);
                pinu(af);
                pinu(ag);
                STAMP3(32);
#pragma unroll
                for (int jb = 0; jb < 4; jb++) {
                    const int i = 8 * jb;
                    c2 s0 = {{za[i], za[i + 4]}, {za[i + 1], za[i + 5]}}, s2 = {{za[i + 2], za[i + 6]}, {za[i + 3], za[i + 7]}};
                    c2 s1 = {{zb[i], zb[i + 4]}, {zb[i + 1], zb[i + 5]}}, s3 = {{zb[i + 2], zb[i + 6]}, {zb[i + 3], zb[i + 7]}};
                    s2 = mul2(s2, be1);
                    fin(s2);
                    bfly_tw(s0, s1, be2, s2, s3, be3);
                    bfly(s0, s2); bfly_mi(s1, s3);
                    c2 W[4];
#pragma unroll
                    for (int j = 0; j < 4; j++) {
                        W[j] = {{__uint_as_float(wr[4 * j] << 16), __uint_as_float(wr[4 * j + 1] << 16)}, {__uint_as_float(wr[4 * j + 2] << 16), __uint_as_float(wr[4 * j + 3] << 16)}};
                        if ((jb & 1) == 0)
                            asm volatile("@p0 ld.shared.v2.f32 {%0,%1}, [%2];" : "+f"(W[j].a.x), "+f"(W[j].a.y) : "r"(sb + OFF_WSP + u * 64 + jb * 16 + j * 8));
                    }
                    if (jb < 3) {
#pragma unroll
                        for (int k = 0; k < 16; k++) {
                            const int e = (k >> 1) & 1, pl = (k & 1) * 4 * WPITCH;
                            wr[k] = jb == 0 ? lds16(wd[k >> 2] + 512 + 256 * e + pl) : lds16(wm[k >> 2] - 512 * (jb - 1) - 256 * e + pl);
                        }
                    }
                    if (jb >= 2) {
#pragma unroll
                        for (int j = 0; j < 4; j++) { W[j].a.y = -W[j].a.y; W[j].b.y = -W[j].b.y; }
                    }
                    s0 = mul2(s0, W[0]); fin(s0);
                    s1 = mul2(s1, W[1]); fin(s1);
                    bfly_tw(s0, s2, W[2], s1, s3, W[3]);
                    bfly(s0, s1); bfly_mi(s2, s3);
                    af[4 * jb] = pk(s0.a.x, s0.b.x); af[4 * jb + 1] = pk(s3.a.x, s3.b.x); af[4 * jb + 2] = pk(s0.a.y, s0.b.y); af[4 * jb + 3] = pk(s3.a.y, s3.b.y);
                    ag[4 * jb] = pk(s1.a.x, s1.b.x); ag[4 * jb + 1] = pk(s2.a.x, s2.b.x); ag[4 * jb + 2] = pk(s1.a.y, s1.b.y); ag[4 * jb + 3] = pk(s2.a.y, s2.b.y);
                }
                pinu(af);
                pinu(ag);
                warp_arrive(bars + B_WFREE);
                wg_fence();
#pragma unroll
                for (int j = 0; j < 4; j++) mma64_rs<1>(ya, af[4 * j], af[4 * j + 1], af[4 * j + 2], af[4 * j + 3], dF + j * 128, j);
                wg_commit();
#pragma unroll
                for (int j = 0; j < 4; j++) mma64_rs<1>(yb, ag[4 * j], ag[4 * j + 1], ag[4 * j + 2], ag[4 * j + 3], dF + j * 128, j);
                wg_commit();
                STAMP3(33);
                {
                    const uint32_t a0 = buf + (mi & 1) * 4096 + (16 * w + 8 * (mi >> 1) + gl) * 64 + ((gl >> 1) << 4);
#pragma unroll
                    for (int h = 0; h < 2; h++) {
                        if (h == 0) { wg_wait<1>(); pin(ya); pinu(af); STAMP3(34); } else { wg_wait<0>(); pin(yb); pinu(ag); }
                        const float(&yy)[32] = h ? yb : ya;
#pragma unroll
                        for (int c = 0; c < 4; c++) {
                            const int i = 8 * ((c + 2 * h) & 3), k = 8 * ((c + 2 * h + 1) & 3) + 2;
                            c2 x = {cmulc({yy[i], yy[i + 1]}, T[2 * c]), cmulc({yy[k], yy[k + 1]}, T[2 * c])};
                            fin(x);
                            c2 y = {cmulc({yy[i + 4], yy[i + 5]}, T[2 * c + 1]), cmulc({yy[k + 4], yy[k + 5]}, T[2 * c + 1])};
                            fin(y);
                            stsm4((a0 ^ (c << 4)) + h * 8192, pk(x.a.x, y.a.x), pk(x.b.x, y.b.x), pk(x.a.y, y.a.y), pk(x.b.y, y.b.y));
                        }
                    }
                }
                STAMP3(38);
                fence_async_sm();
                bar_sync(3, 128);
                wg_fence();
#pragma unroll
                for (int j = 0; j < 4; j++) mma128_ss<0, 1, 1>(vv, dF + j * 128, dB + j * 64, j);
                wg_commit();
                STAMP3(35);
                uint32_t va = buf + (8 * w + (g >> 1)) * 64 + (g & 1) * 32 + (((q ^ (slot >> 1)) & 1) << 4) + (q >> 1) * 8, vb = va;
                if (kap == 256) { if (g & 1) vb -= 16384; else va -= 16384 - 32; }
                const uint32_t tmask = ((g & 1) == ((slot >> 3) & 1) && q == ((slot >> 1) & 2)) ? ~1u : ~0u, tbit = ep & ~tmask;
                wg_wait<0>();
                pin(vv);
                STAMP3(36);
                bar_sync(3, 128);
#pragma unroll
                for (int k = 0; k < 16; k++) {
                    const int b = k >> 2, hh = (k >> 1) & 1, h = k & 1, i = 16 * b + 8 * hh + 2 * h;
                    sts64((b ? vb : va) + hh * 8192 + b * 2048 + h * 256, (pk(vv[i], vv[i + 1]) & tmask) | tbit, pk(vv[i + 4], vv[i + 5]));
                }
                fence_async_sm();
                warp_arrive(bars + B_STG);
            }
        }
        if (spare) return;
        }
        {
            uint32_t sp[8];
            cf tw[8];
            ldtab<2, 2048>(sp, TAB_SP + fb * 4096 + t7 * 16);
            ldtab_cf<16>(tw, TAB_TW3 + fb * 2048 + (t7 >> 2) * 64);
            const uint64_t dF = opaque(mkdesc(sb + OFF_F, 16, 1024, 1)), dB = opaque(mkdesc(sb + OFF_P + hf * 8192, 1024, 256, 3));
            const uint8_t* op = padd(p.out + (1024 + fb) * 2048 + fcb * 32 + hf * 16, (t7 >> 2) * 32768 + (q >> 1) * 16 + (q & 1) * 32);
            float acc[64], out[64];
            mbar_wait(bars + B_IN + 24, 0);
            mbar_wait(bars + B_FG, 1);
            STAMP(25);
            pinu(sp);
            wg_fence();
#pragma unroll
            for (int j = 0; j < 4; j++) {
                const uint64_t db = dB + (j >> 1) * 1024 + (j & 1) * 32;
                mma112_ss(acc, dF + j * 2, db + 64, j);
                if (j & 1) mma16_rs(acc, 0u, sp[2 * j], 0u, sp[2 * j + 1], db, 1);
                else mma16_rs(acc, sp[2 * j], 0u, sp[2 * j + 1], 0u, db, j);
            }
            wg_commit();
            wg_wait<0>();
            pin(acc);
            pinu(sp);
            warp_arrive(bars + B_P3M);
#pragma unroll
            for (int cl = 0; cl < 2; cl++) {
                c2 z[8];
#pragma unroll
                for (int n = 0; n < 8; n++) {
                    const int i = 4 * (2 * n + cl);
                    z[n] = {{acc[i], acc[i + 2]}, {acc[i + 1], acc[i + 3]}};
                }
                z[0] = {{z[0].a.x + z[0].a.y, z[0].a.x - z[0].a.y}, {z[0].b.x + z[0].b.y, z[0].b.x - z[0].b.y}};
                z[4] = mul2(z[4], tw[4]);
                fin(z[0], z[4]);
#pragma unroll
                for (int n = 1; n < 4; n++) {
                    const cf iw = n == 1 ? cf{0.38268343236508977f, 0.92387953251128674f}
                                         : (n == 2 ? cf{0.70710678118654752f, 0.70710678118654752f} : cf{0.92387953251128674f, 0.38268343236508977f});
                    c2 y = mul2(z[n], tw[n]);
                    fin(y);
                    const cf t = {tw[8 - n].x, -tw[8 - n].y};
                    c2 E = fma2(c2{{z[8 - n].a.x, -z[8 - n].a.y}, {z[8 - n].b.x, -z[8 - n].b.y}}, t, y);
                    fin(E);
                    z[n] = fma2(twm2(y, E), iw, E);
                    fin(z[n]);
                    z[8 - n] = {{fmaf(2.f, E.a.x, -z[n].a.x), fmaf(-2.f, E.a.y, z[n].a.y)}, {fmaf(2.f, E.b.x, -z[n].b.x), fmaf(-2.f, E.b.y, z[n].b.y)}};
                }
                dft8<false>(z, tw);
#pragma unroll
                for (int m = 0; m < 8; m++) {
                    out[8 * m + 2 * cl] = z[m].a.x; out[8 * m + 2 * cl + 1] = z[m].b.x;
                    out[8 * m + 4 + 2 * cl] = z[m].a.y; out[8 * m + 5 + 2 * cl] = z[m].b.y;
                }
            }
            STAMP(26);
#pragma unroll
            for (int m = 0; m < 16; m++) {
                asm volatile("st.global.v4.f32 [%0], {%1,%2,%3,%4};" ::"l"(op + (m - 8) * (1 << 20)), "f"(out[4 * m]), "f"(out[4 * m + 1]), "f"(out[4 * m + 2]), "f"(out[4 * m + 3]) : "memory");
                if (PACE_O && m < 15 && m % PACE_ON == PACE_ON - 1)
                    asm volatile("{.reg .pred p; mbarrier.test_wait.parity.shared::cta.b64 p, [%0], 0; @!p nanosleep.u32 %1;}" ::"r"(bars + B_DONE), "n"(PACE_O) : "memory");
            }
            STAMP(27);
        }
    }
}

typedef CUresult (*EncodeFn)(CUtensorMap*, CUtensorMapDataType, cuuint32_t, void*, const cuuint64_t*, const cuuint64_t*, const cuuint32_t*,
                             const cuuint32_t*, CUtensorMapInterleave, CUtensorMapSwizzle, CUtensorMapL2promotion, CUtensorMapFloatOOBfill);

static CUtensorMap make_map(EncodeFn enc, const void* ptr, int rank, const cuuint64_t* dims, const cuuint64_t* strides, const cuuint32_t* box,
                            CUtensorMapSwizzle swz, CUtensorMapL2promotion promo, CUtensorMapDataType dt = CU_TENSOR_MAP_DATA_TYPE_BFLOAT16) {
    CUtensorMap m;
    const cuuint32_t es[5] = {1, 1, 1, 1, 1};
    enc(&m, dt, rank, const_cast<void*>(ptr), dims, strides, box, es, CU_TENSOR_MAP_INTERLEAVE_NONE, swz, promo,
        CU_TENSOR_MAP_FLOAT_OOB_FILL_NONE);
    return m;
}

extern "C" void kernel_launch(void* const* d_in, const int* in_sizes, int n_in, void* d_out, int out_size) {
    void* fn = nullptr;
    cudaDriverEntryPointQueryResult qr;
    cudaGetDriverEntryPoint("cuTensorMapEncodeTiled", &fn, cudaEnableDefault, &qr);
    EncodeFn enc = (EncodeFn)fn;
    void* pX;
    cudaGetSymbolAddress(&pX, g_X);
    const CUtensorMapL2promotion P256 = CU_TENSOR_MAP_L2_PROMOTION_L2_256B, P0 = CU_TENSOR_MAP_L2_PROMOTION_NONE;

    const cuuint64_t dX[5] = {1024, 2, 4, 16, 16}, sX[4] = {2048, 32 * 2048, 2 * 2048, 128 * 2048};
    const cuuint32_t bX[5] = {64, 2, 4, 16, 1};
    CUtensorMap tmX = make_map(enc, d_in[3], 5, dX, sX, bX, CU_TENSOR_MAP_SWIZZLE_128B, P256);
    const cuuint64_t dXd[4] = {64, 2048, 2, 16}, sXd[3] = {2048, 64 * 2048, 128};
    const cuuint32_t bXd[4] = {64, 16, 2, 2};
    CUtensorMap tmXd = make_map(enc, d_in[3], 4, dXd, sXd, bXd, CU_TENSOR_MAP_SWIZZLE_128B, P256);
    const cuuint64_t dB[4] = {1024, 8, 4, 32}, sB[3] = {2048, 256 * 2048, 8 * 2048};
    const cuuint32_t bB4[4] = {64, 8, 2, 4};
    CUtensorMap tmBre = make_map(enc, d_in[6], 4, dB, sB, bB4, CU_TENSOR_MAP_SWIZZLE_128B, P256);
    CUtensorMap tmBim = make_map(enc, d_in[7], 4, dB, sB, bB4, CU_TENSOR_MAP_SWIZZLE_128B, P256);
    const cuuint64_t dC[5] = {1024, 2, 4, 2, 64}, sC[4] = {2048, 4 * 2048, 2 * 2048, 16 * 2048};
    const cuuint32_t bC[5] = {64, 2, 4, 2, 4};
    CUtensorMap tmCre = make_map(enc, d_in[8], 5, dC, sC, bC, CU_TENSOR_MAP_SWIZZLE_128B, P256);
    CUtensorMap tmCim = make_map(enc, d_in[9], 5, dC, sC, bC, CU_TENSOR_MAP_SWIZZLE_128B, P256);

    const cuuint64_t dU[2] = {8192, 256}, sU[1] = {16384}, dV[2] = {16384, 128}, sV[1] = {32768};
    const cuuint32_t bU[2] = {64, 64}, bV[2] = {32, 128};
    CUtensorMap tmUst = make_map(enc, pX, 2, dU, sU, bU, CU_TENSOR_MAP_SWIZZLE_128B, P0);
    CUtensorMap tmVst = make_map(enc, (uint8_t*)pX + (4 << 20), 2, dV, sV, bV, CU_TENSOR_MAP_SWIZZLE_NONE, P0);
    const cuuint64_t dF[2] = {512 * 1026 / 8, 4}, sF[1] = {512 * 1026};
    const cuuint32_t bF[2] = {WPITCH / 8, 4};
    CUtensorMap tmWr = make_map(enc, d_in[1], 2, dF, sF, bF, CU_TENSOR_MAP_SWIZZLE_NONE, P0, CU_TENSOR_MAP_DATA_TYPE_UINT64);
    CUtensorMap tmWi = make_map(enc, d_in[2], 2, dF, sF, bF, CU_TENSOR_MAP_SWIZZLE_NONE, P0, CU_TENSOR_MAP_DATA_TYPE_UINT64);

    const cuuint64_t dA[3] = {1024, 64, 32}, sA[2] = {32 * 2048, 2048};
    const cuuint32_t bA[3] = {32, 64, 1};
    CUtensorMap tmXa = make_map(enc, d_in[0], 3, dA, sA, bA, CU_TENSOR_MAP_SWIZZLE_64B, XA_PROMO);

    Params p;
    p.wr = (const __nv_bfloat16*)d_in[1];
    p.wi = (const __nv_bfloat16*)d_in[2];
    p.lre = (const __nv_bfloat16*)d_in[4];
    p.lim = (const __nv_bfloat16*)d_in[5];
    p.ldt = (const __nv_bfloat16*)d_in[10];
    p.dsk = (const __nv_bfloat16*)d_in[11];
    p.out = (float*)d_out;
    int dev = 0, sms = 0;
    cudaGetDevice(&dev);
    cudaDeviceGetAttribute(&sms, cudaDevAttrMultiProcessorCount, dev);
    auto kernel = sms == 132 ? fused_kernel<true> : fused_kernel<false>;
    cudaFuncSetAttribute(kernel, cudaFuncAttributeMaxDynamicSharedMemorySize, SMEM_BYTES);
    kernel<<<132, 512, SMEM_BYTES>>>(tmX, tmBre, tmBim, tmCre, tmCim, tmXd, tmUst, tmVst, tmWr, tmWi, tmXa, p);
}
```

```cpp
#include <cuda_runtime.h>
#include <cuda.h>
#include <cuda_bf16.h>
#include <stdint.h>

#define NST 5
#define WPITCH 1056
#define OFF_P (NST * 32768)
#define OFF_F (OFF_P + 32768)
#define OFF_WD (OFF_F + 8192)
#define OFF_WM (OFF_WD + 8 * WPITCH)
#define OFF_BAR (OFF_F + 32768)
#define OFF_LAM (OFF_BAR + 432)
#define OFF_WSP (OFF_LAM + 2048)
#define OFF_PROF (OFF_WSP + 128)
#define SMEM_BYTES OFF_PROF
#define B_FULL 0
#define B_HL 40
#define B_EP 120
#define B_HR 128
#define B_XD 144
#define B_FG 160
#define B_WSP 168
#define B_WD 176
#define B_DONE 184
#define B_LD 192
#define B_RAW 200
#define B_LAM 208
#define B_IN 216
#define B_XIN 248
#define B_EMPTY 256
#define B_STG 320
#define B_WFREE 328
#define B_HOWN 336
#define B_STGU 368
#define B_P3M 384
#define B_GOV 400
#define B_EPOCH 416

#define PACE_U 20
#define PACE_V 20
#define XA_PACE 200
#define XA_PACE2 100
#define XA_TAB 0
#define XA_TABP 200
#define PACE_O 200
#define PACE_ON 1
#define XA_PROMO CU_TENSOR_MAP_L2_PROMOTION_L2_128B
#define TAB_T0 500
#define LAM_T0 1000
#define DEFER 0
#define UHINT 1
#define VPOS 2
#define VPOS0 8
#define GOV_T 100
#define GOV_K0 16
#define GOV_N 22
#define TIDMAP threadIdx.x
#define XA_N0 2
#define XA_T0 0
#define PACE_X 200
#define SKEW 4
#define SPIN_LIMIT (1u << 15)

__device__ __align__(1024) uint8_t g_X[8 << 20];
__device__ __align__(1024) uint8_t g_H[8 << 20];
__device__ __align__(1024) uint4 g_carry[16 * 512];
__device__ __align__(128) unsigned g_cnt[128 + 8 * 32];
__device__ __align__(128) unsigned g_epoch[132 * 8];

#define STAMP(i) do { } while (0)
#define STAMPO(i, o) do { } while (0)
#define STAMPW(a, b) do { } while (0)
#define STAMPX(a, b) do { } while (0)
#define STAMP5(i) do { } while (0)
#define STAMP6(i) do { } while (0)
#define STAMP3(i) do { } while (0)

#define TAB_FG 0
#define TAB_G 8192
#define TAB_F1 40960
#define TAB_T 49152
#define TAB_SP 57344
#define TAB_TW1 73728
#define TAB_TW3 75776
#define TAB_PC 83968
__device__ __align__(1024) const uint32_t g_tab[21248] = {
0x80003d80,0x80003d80,0x80003d80,0x80003d80,0x80003d80,0x80003d80,0x80003d80,0x80003d80,0x80003d80,0x80003d80,0x80003d80,0x80003d80,0x80003d80,0x80003d80,0x80003d80,0x80003d80,
0x80003d80,0x80003d80,0x80003d80,0x80003d80,0x80003d80,0x80003d80,0x80003d80,0x80003d80,0x80003d80,0x80003d80,0x80003d80,0x80003d80,0x80003d80,0x80003d80,0x80003d80,0x80003d80,
0x3d353d35,0x3d35bd35,0xbd35bd35,0xbd353d35,0x80003d80,0x3d800000,0x8000bd80,0xbd800000,0x3d353d35,0x3d35bd35,0xbd35bd35,0xbd353d35,0x80003d80,0x3d800000,0x8000bd80,0xbd800000,
0x3d353d35,0x3d35bd35,0xbd35bd35,0xbd353d35,0x80003d80,0x3d800000,0x8000bd80,0xbd800000,0x3d353d35,0x3d35bd35,0xbd35bd35,0xbd353d35,0x80003d80,0x3d800000,0x8000bd80,0xbd800000,
0x3d800000,0x3d6dbcc4,0x3d35bd35,0x3cc4bd6d,0x3d7bbc48,0x3d55bd0e,0x3d0ebd55,0x3c48bd7b,0x80003d80,0x3cc43d6d,0x3d353d35,0x3d6d3cc4,0x3c483d7b,0x3d0e3d55,0x3d553d0e,0x3d7b3c48,
0xbd800000,0xbd6d3cc4,0xbd353d35,0xbcc43d6d,0xbd7b3c48,0xbd553d0e,0xbd0e3d55,0xbc483d7b,0x8000bd80,0xbcc4bd6d,0xbd35bd35,0xbd6dbcc4,0xbc48bd7b,0xbd0ebd55,0xbd55bd0e,0xbd7bbc48,
0x3d0ebd55,0xbd7bbc48,0x3c483d7b,0x3d55bd0e,0x3d800000,0xbcc4bd6d,0xbd353d35,0x3d6d3cc4,0x3d553d0e,0x3c48bd7b,0xbd7b3c48,0x3d0e3d55,0x80003d80,0x3d6dbcc4,0xbd35bd35,0xbcc43d6d,
0xbd0e3d55,0x3d7b3c48,0xbc48bd7b,0xbd553d0e,0xbd800000,0x3cc43d6d,0x3d35bd35,0xbd6dbcc4,0xbd55bd0e,0xbc483d7b,0x3d7bbc48,0xbd0ebd55,0x8000bd80,0xbd6d3cc4,0x3d353d35,0x3cc4bd6d,
0x80003d80,0x3d353d35,0x3d800000,0x3d35bd35,0x3cc43d6d,0x3d6d3cc4,0x3d6dbcc4,0x3cc4bd6d,0x8000bd80,0xbd35bd35,0xbd800000,0xbd353d35,0xbcc4bd6d,0xbd6dbcc4,0xbd6d3cc4,0xbcc43d6d,
0x80003d80,0x3d353d35,0x3d800000,0x3d35bd35,0x3cc43d6d,0x3d6d3cc4,0x3d6dbcc4,0x3cc4bd6d,0x8000bd80,0xbd35bd35,0xbd800000,0xbd353d35,0xbcc4bd6d,0xbd6dbcc4,0xbd6d3cc4,0xbcc43d6d,
0x3d6d3cc4,0xbcc4bd6d,0xbcc43d6d,0x3d6dbcc4,0x80003d80,0x3d35bd35,0xbd800000,0x3d353d35,0xbd6dbcc4,0x3cc43d6d,0x3cc4bd6d,0xbd6d3cc4,0x8000bd80,0xbd353d35,0x3d800000,0xbd35bd35,
0x3d6d3cc4,0xbcc4bd6d,0xbcc43d6d,0x3d6dbcc4,0x80003d80,0x3d35bd35,0xbd800000,0x3d353d35,0xbd6dbcc4,0x3cc43d6d,0x3cc4bd6d,0xbd6d3cc4,0x8000bd80,0xbd353d35,0x3d800000,0xbd35bd35,
0x3d800000,0x3cc4bd6d,0xbd35bd35,0xbd6d3cc4,0x3d55bd0e,0xbc48bd7b,0xbd7bbc48,0xbd0e3d55,0x8000bd80,0xbd6dbcc4,0xbd353d35,0x3cc43d6d,0xbd0ebd55,0xbd7b3c48,0xbc483d7b,0x3d553d0e,
0xbd800000,0xbcc43d6d,0x3d353d35,0x3d6dbcc4,0xbd553d0e,0x3c483d7b,0x3d7b3c48,0x3d0ebd55,0x80003d80,0x3d6d3cc4,0x3d35bd35,0xbcc4bd6d,0x3d0e3d55,0x3d7bbc48,0x3c48bd7b,0xbd55bd0e,
0x3c48bd7b,0xbd0e3d55,0x3d55bd0e,0xbd7b3c48,0x3d800000,0xbd6dbcc4,0x3d353d35,0xbcc4bd6d,0xbd7bbc48,0x3d553d0e,0xbd0ebd55,0x3c483d7b,0x8000bd80,0xbcc43d6d,0x3d35bd35,0xbd6d3cc4,
0xbc483d7b,0x3d0ebd55,0xbd553d0e,0x3d7bbc48,0xbd800000,0x3d6d3cc4,0xbd35bd35,0x3cc43d6d,0x3d7b3c48,0xbd55bd0e,0x3d0e3d55,0xbc48bd7b,0x80003d80,0x3cc4bd6d,0xbd353d35,0x3d6dbcc4,
0x3d800000,0x3d800000,0x3d800000,0x3d800000,0x3d800000,0x3d800000,0x3d800000,0x3d800000,0x3d800000,0x3d800000,0x3d800000,0x3d800000,0x3d800000,0x3d800000,0x3d800000,0x3d800000,
0x3d800000,0x3d800000,0x3d800000,0x3d800000,0x3d800000,0x3d800000,0x3d800000,0x3d800000,0x3d800000,0x3d800000,0x3d800000,0x3d800000,0x3d800000,0x3d800000,0x3d800000,0x3d800000,
0x3d35bd35,0xbd35bd35,0xbd353d35,0x3d353d35,0x3d800000,0xbd80,0xbd800000,0x3d80,0x3d35bd35,0xbd35bd35,0xbd353d35,0x3d353d35,0x3d800000,0xbd80,0xbd800000,0x3d80,
0x3d35bd35,0xbd35bd35,0xbd353d35,0x3d353d35,0x3d800000,0xbd80,0xbd800000,0x3d80,0x3d35bd35,0xbd35bd35,0xbd353d35,0x3d353d35,0x3d800000,0xbd80,0xbd800000,0x3d80,
0xbd80,0xbcc4bd6d,0xbd35bd35,0xbd6dbcc4,0xbc48bd7b,0xbd0ebd55,0xbd55bd0e,0xbd7bbc48,0x3d800000,0x3d6dbcc4,0x3d35bd35,0x3cc4bd6d,0x3d7bbc48,0x3d55bd0e,0x3d0ebd55,0x3c48bd7b,
0x3d80,0x3cc43d6d,0x3d353d35,0x3d6d3cc4,0x3c483d7b,0x3d0e3d55,0x3d553d0e,0x3d7b3c48,0xbd800000,0xbd6d3cc4,0xbd353d35,0xbcc43d6d,0xbd7b3c48,0xbd553d0e,0xbd0e3d55,0xbc483d7b,
0xbd55bd0e,0xbc483d7b,0x3d7bbc48,0xbd0ebd55,0xbd80,0xbd6d3cc4,0x3d353d35,0x3cc4bd6d,0x3d0ebd55,0xbd7bbc48,0x3c483d7b,0x3d55bd0e,0x3d800000,0xbcc4bd6d,0xbd353d35,0x3d6d3cc4,
0x3d553d0e,0x3c48bd7b,0xbd7b3c48,0x3d0e3d55,0x3d80,0x3d6dbcc4,0xbd35bd35,0xbcc43d6d,0xbd0e3d55,0x3d7b3c48,0xbc48bd7b,0xbd553d0e,0xbd800000,0x3cc43d6d,0x3d35bd35,0xbd6dbcc4,
0x3d800000,0x3d35bd35,0xbd80,0xbd35bd35,0x3d6dbcc4,0x3cc4bd6d,0xbcc4bd6d,0xbd6dbcc4,0xbd800000,0xbd353d35,0x3d80,0x3d353d35,0xbd6d3cc4,0xbcc43d6d,0x3cc43d6d,0x3d6d3cc4,
0x3d800000,0x3d35bd35,0xbd80,0xbd35bd35,0x3d6dbcc4,0x3cc4bd6d,0xbcc4bd6d,0xbd6dbcc4,0xbd800000,0xbd353d35,0x3d80,0x3d353d35,0xbd6d3cc4,0xbcc43d6d,0x3cc43d6d,0x3d6d3cc4,
0x3cc4bd6d,0xbd6d3cc4,0x3d6d3cc4,0xbcc4bd6d,0x3d800000,0xbd35bd35,0x3d80,0x3d35bd35,0xbcc43d6d,0x3d6dbcc4,0xbd6dbcc4,0x3cc43d6d,0xbd800000,0x3d353d35,0xbd80,0xbd353d35,
0x3cc4bd6d,0xbd6d3cc4,0x3d6d3cc4,0xbcc4bd6d,0x3d800000,0xbd35bd35,0x3d80,0x3d35bd35,0xbcc43d6d,0x3d6dbcc4,0xbd6dbcc4,0x3cc43d6d,0xbd800000,0x3d353d35,0xbd80,0xbd353d35,
0xbd80,0xbd6dbcc4,0xbd353d35,0x3cc43d6d,0xbd0ebd55,0xbd7b3c48,0xbc483d7b,0x3d553d0e,0xbd800000,0xbcc43d6d,0x3d353d35,0x3d6dbcc4,0xbd553d0e,0x3c483d7b,0x3d7b3c48,0x3d0ebd55,
0x3d80,0x3d6d3cc4,0x3d35bd35,0xbcc4bd6d,0x3d0e3d55,0x3d7bbc48,0x3c48bd7b,0xbd55bd0e,0x3d800000,0x3cc4bd6d,0xbd35bd35,0xbd6d3cc4,0x3d55bd0e,0xbc48bd7b,0xbd7bbc48,0xbd0e3d55,
0xbd7bbc48,0x3d553d0e,0xbd0ebd55,0x3c483d7b,0xbd80,0xbcc43d6d,0x3d35bd35,0xbd6d3cc4,0xbc483d7b,0x3d0ebd55,0xbd553d0e,0x3d7bbc48,0xbd800000,0x3d6d3cc4,0xbd35bd35,0x3cc43d6d,
0x3d7b3c48,0xbd55bd0e,0x3d0e3d55,0xbc48bd7b,0x3d80,0x3cc4bd6d,0xbd353d35,0x3d6dbcc4,0x3c48bd7b,0xbd0e3d55,0x3d55bd0e,0xbd7b3c48,0x3d800000,0xbd6dbcc4,0x3d353d35,0xbcc4bd6d,
0x80003d80,0x8000bd80,0x80003d80,0x8000bd80,0x3d800000,0xbd800000,0x3d800000,0xbd800000,0x80003d80,0x8000bd80,0x80003d80,0x8000bd80,0x3d800000,0xbd800000,0x3d800000,0xbd800000,
0x80003d80,0x8000bd80,0x80003d80,0x8000bd80,0x3d800000,0xbd800000,0x3d800000,0xbd800000,0x80003d80,0x8000bd80,0x80003d80,0x8000bd80,0x3d800000,0xbd800000,0x3d800000,0xbd800000,
0x3d35bd35,0x3d353d35,0xbd353d35,0xbd35bd35,0x80003d80,0xbd800000,0x8000bd80,0x3d800000,0x3d35bd35,0x3d353d35,0xbd353d35,0xbd35bd35,0x80003d80,0xbd800000,0x8000bd80,0x3d800000,
0x3d35bd35,0x3d353d35,0xbd353d35,0xbd35bd35,0x80003d80,0xbd800000,0x8000bd80,0x3d800000,0x3d35bd35,0x3d353d35,0xbd353d35,0xbd35bd35,0x80003d80,0xbd800000,0x8000bd80,0x3d800000,
0x3d800000,0xbd6d3cc4,0x3d35bd35,0xbcc43d6d,0xbc48bd7b,0x3d0e3d55,0xbd55bd0e,0x3d7b3c48,0x80003d80,0xbcc4bd6d,0x3d353d35,0xbd6dbcc4,0x3d7bbc48,0xbd553d0e,0x3d0ebd55,0xbc483d7b,
0xbd800000,0x3d6dbcc4,0xbd353d35,0x3cc4bd6d,0x3c483d7b,0xbd0ebd55,0x3d553d0e,0xbd7bbc48,0x8000bd80,0x3cc43d6d,0xbd35bd35,0x3d6d3cc4,0xbd7b3c48,0x3d55bd0e,0xbd0e3d55,0x3c48bd7b,
0xbd55bd0e,0x3c48bd7b,0x3d7bbc48,0x3d0e3d55,0x3d800000,0x3cc43d6d,0xbd353d35,0xbd6dbcc4,0x3d0ebd55,0x3d7b3c48,0x3c483d7b,0xbd553d0e,0x80003d80,0xbd6d3cc4,0xbd35bd35,0x3cc4bd6d,
0x3d553d0e,0xbc483d7b,0xbd7b3c48,0xbd0ebd55,0xbd800000,0xbcc4bd6d,0x3d35bd35,0x3d6d3cc4,0xbd0e3d55,0xbd7bbc48,0xbc48bd7b,0x3d55bd0e,0x8000bd80,0x3d6dbcc4,0x3d353d35,0xbcc43d6d,
0x80003d80,0xbd35bd35,0x3d800000,0xbd353d35,0x3d6dbcc4,0xbcc43d6d,0xbcc4bd6d,0x3d6d3cc4,0x8000bd80,0x3d353d35,0xbd800000,0x3d35bd35,0xbd6d3cc4,0x3cc4bd6d,0x3cc43d6d,0xbd6dbcc4,
0x80003d80,0xbd35bd35,0x3d800000,0xbd353d35,0x3d6dbcc4,0xbcc43d6d,0xbcc4bd6d,0x3d6d3cc4,0x8000bd80,0x3d353d35,0xbd800000,0x3d35bd35,0xbd6d3cc4,0x3cc4bd6d,0x3cc43d6d,0xbd6dbcc4,
0x3cc4bd6d,0x3d6dbcc4,0x3d6d3cc4,0x3cc43d6d,0x80003d80,0xbd353d35,0xbd800000,0xbd35bd35,0xbcc43d6d,0xbd6d3cc4,0xbd6dbcc4,0xbcc4bd6d,0x8000bd80,0x3d35bd35,0x3d800000,0x3d353d35,
0x3cc4bd6d,0x3d6dbcc4,0x3d6d3cc4,0x3cc43d6d,0x80003d80,0xbd353d35,0xbd800000,0xbd35bd35,0xbcc43d6d,0xbd6d3cc4,0xbd6dbcc4,0xbcc4bd6d,0x8000bd80,0x3d35bd35,0x3d800000,0x3d353d35,
0x3d800000,0xbcc43d6d,0xbd35bd35,0x3d6dbcc4,0xbd0ebd55,0x3d7bbc48,0xbc483d7b,0xbd55bd0e,0x8000bd80,0x3d6d3cc4,0xbd353d35,0xbcc4bd6d,0xbd553d0e,0xbc48bd7b,0x3d7b3c48,0xbd0e3d55,
0xbd800000,0x3cc4bd6d,0x3d353d35,0xbd6d3cc4,0x3d0e3d55,0xbd7b3c48,0x3c48bd7b,0x3d553d0e,0x80003d80,0xbd6dbcc4,0x3d35bd35,0x3cc43d6d,0x3d55bd0e,0x3c483d7b,0xbd7bbc48,0x3d0ebd55,
0xbd7bbc48,0xbd55bd0e,0xbd0ebd55,0xbc48bd7b,0x3d800000,0x3d6d3cc4,0x3d353d35,0x3cc43d6d,0xbc483d7b,0xbd0e3d55,0xbd553d0e,0xbd7b3c48,0x8000bd80,0x3cc4bd6d,0x3d35bd35,0x3d6dbcc4,
0x3d7b3c48,0x3d553d0e,0x3d0e3d55,0x3c483d7b,0xbd800000,0xbd6dbcc4,0xbd35bd35,0xbcc4bd6d,0x3c48bd7b,0x3d0ebd55,0x3d55bd0e,0x3d7bbc48,0x80003d80,0xbcc43d6d,0xbd353d35,0xbd6d3cc4,
0x3d800000,0xbd800000,0x3d800000,0xbd800000,0xbd80,0x3d80,0xbd80,0x3d80,0x3d800000,0xbd800000,0x3d800000,0xbd800000,0xbd80,0x3d80,0xbd80,0x3d80,
0x3d800000,0xbd800000,0x3d800000,0xbd800000,0xbd80,0x3d80,0xbd80,0x3d80,0x3d800000,0xbd800000,0x3d800000,0xbd800000,0xbd80,0x3d80,0xbd80,0x3d80,
0xbd35bd35,0x3d35bd35,0x3d353d35,0xbd353d35,0x3d800000,0x3d80,0xbd800000,0xbd80,0xbd35bd35,0x3d35bd35,0x3d353d35,0xbd353d35,0x3d800000,0x3d80,0xbd800000,0xbd80,
0xbd35bd35,0x3d35bd35,0x3d353d35,0xbd353d35,0x3d800000,0x3d80,0xbd800000,0xbd80,0xbd35bd35,0x3d35bd35,0x3d353d35,0xbd353d35,0x3d800000,0x3d80,0xbd800000,0xbd80,
0xbd80,0x3cc43d6d,0xbd35bd35,0x3d6d3cc4,0xbd7b3c48,0x3d55bd0e,0xbd0e3d55,0x3c48bd7b,0x3d800000,0xbd6d3cc4,0x3d35bd35,0xbcc43d6d,0xbc48bd7b,0x3d0e3d55,0xbd55bd0e,0x3d7b3c48,
0x3d80,0xbcc4bd6d,0x3d353d35,0xbd6dbcc4,0x3d7bbc48,0xbd553d0e,0x3d0ebd55,0xbc483d7b,0xbd800000,0x3d6dbcc4,0xbd353d35,0x3cc4bd6d,0x3c483d7b,0xbd0ebd55,0x3d553d0e,0xbd7bbc48,
0xbd0e3d55,0xbd7bbc48,0xbc48bd7b,0x3d55bd0e,0xbd80,0x3d6dbcc4,0x3d353d35,0xbcc43d6d,0xbd55bd0e,0x3c48bd7b,0x3d7bbc48,0x3d0e3d55,0x3d800000,0x3cc43d6d,0xbd353d35,0xbd6dbcc4,
0x3d0ebd55,0x3d7b3c48,0x3c483d7b,0xbd553d0e,0x3d80,0xbd6d3cc4,0xbd35bd35,0x3cc4bd6d,0x3d553d0e,0xbc483d7b,0xbd7b3c48,0xbd0ebd55,0xbd800000,0xbcc4bd6d,0x3d35bd35,0x3d6d3cc4,
0x3d800000,0xbd353d35,0xbd80,0x3d353d35,0xbcc4bd6d,0x3d6d3cc4,0xbd6d3cc4,0x3cc4bd6d,0xbd800000,0x3d35bd35,0x3d80,0xbd35bd35,0x3cc43d6d,0xbd6dbcc4,0x3d6dbcc4,0xbcc43d6d,
0x3d800000,0xbd353d35,0xbd80,0x3d353d35,0xbcc4bd6d,0x3d6d3cc4,0xbd6d3cc4,0x3cc4bd6d,0xbd800000,0x3d35bd35,0x3d80,0xbd35bd35,0x3cc43d6d,0xbd6dbcc4,0x3d6dbcc4,0xbcc43d6d,
0xbd6dbcc4,0xbcc4bd6d,0x3cc4bd6d,0x3d6dbcc4,0x3d800000,0x3d353d35,0x3d80,0xbd353d35,0x3d6d3cc4,0x3cc43d6d,0xbcc43d6d,0xbd6d3cc4,0xbd800000,0xbd35bd35,0xbd80,0x3d35bd35,
0xbd6dbcc4,0xbcc4bd6d,0x3cc4bd6d,0x3d6dbcc4,0x3d800000,0x3d353d35,0x3d80,0xbd353d35,0x3d6d3cc4,0x3cc43d6d,0xbcc43d6d,0xbd6d3cc4,0xbd800000,0xbd35bd35,0xbd80,0x3d35bd35,
0xbd80,0x3d6d3cc4,0xbd353d35,0xbcc4bd6d,0xbd553d0e,0xbc48bd7b,0x3d7b3c48,0xbd0e3d55,0xbd800000,0x3cc4bd6d,0x3d353d35,0xbd6d3cc4,0x3d0e3d55,0xbd7b3c48,0x3c48bd7b,0x3d553d0e,
0x3d80,0xbd6dbcc4,0x3d35bd35,0x3cc43d6d,0x3d55bd0e,0x3c483d7b,0xbd7bbc48,0x3d0ebd55,0x3d800000,0xbcc43d6d,0xbd35bd35,0x3d6dbcc4,0xbd0ebd55,0x3d7bbc48,0xbc483d7b,0xbd55bd0e,
0xbc483d7b,0xbd0e3d55,0xbd553d0e,0xbd7b3c48,0xbd80,0x3cc4bd6d,0x3d35bd35,0x3d6dbcc4,0x3d7b3c48,0x3d553d0e,0x3d0e3d55,0x3c483d7b,0xbd800000,0xbd6dbcc4,0xbd35bd35,0xbcc4bd6d,
0x3c48bd7b,0x3d0ebd55,0x3d55bd0e,0x3d7bbc48,0x3d80,0xbcc43d6d,0xbd353d35,0xbd6d3cc4,0xbd7bbc48,0xbd55bd0e,0xbd0ebd55,0xbc48bd7b,0x3d800000,0x3d6d3cc4,0x3d353d35,0x3cc43d6d,
0x80003d80,0x80003d80,0x80003d80,0x80003d80,0x8000bd80,0x8000bd80,0x8000bd80,0x8000bd80,0x80003d80,0x80003d80,0x80003d80,0x80003d80,0x8000bd80,0x8000bd80,0x8000bd80,0x8000bd80,
0x80003d80,0x80003d80,0x80003d80,0x80003d80,0x8000bd80,0x8000bd80,0x8000bd80,0x8000bd80,0x80003d80,0x80003d80,0x80003d80,0x80003d80,0x8000bd80,0x8000bd80,0x8000bd80,0x8000bd80,
0xbd35bd35,0xbd353d35,0x3d353d35,0x3d35bd35,0x80003d80,0x3d800000,0x8000bd80,0xbd800000,0xbd35bd35,0xbd353d35,0x3d353d35,0x3d35bd35,0x80003d80,0x3d800000,0x8000bd80,0xbd800000,
0xbd35bd35,0xbd353d35,0x3d353d35,0x3d35bd35,0x80003d80,0x3d800000,0x8000bd80,0xbd800000,0xbd35bd35,0xbd353d35,0x3d353d35,0x3d35bd35,0x80003d80,0x3d800000,0x8000bd80,0xbd800000,
0x3d800000,0x3d6dbcc4,0x3d35bd35,0x3cc4bd6d,0xbd7b3c48,0xbd553d0e,0xbd0e3d55,0xbc483d7b,0x80003d80,0x3cc43d6d,0x3d353d35,0x3d6d3cc4,0xbc48bd7b,0xbd0ebd55,0xbd55bd0e,0xbd7bbc48,
0xbd800000,0xbd6d3cc4,0xbd353d35,0xbcc43d6d,0x3d7bbc48,0x3d55bd0e,0x3d0ebd55,0x3c48bd7b,0x8000bd80,0xbcc4bd6d,0xbd35bd35,0xbd6dbcc4,0x3c483d7b,0x3d0e3d55,0x3d553d0e,0x3d7b3c48,
0xbd0e3d55,0x3d7b3c48,0xbc48bd7b,0xbd553d0e,0x3d800000,0xbcc4bd6d,0xbd353d35,0x3d6d3cc4,0xbd55bd0e,0xbc483d7b,0x3d7bbc48,0xbd0ebd55,0x80003d80,0x3d6dbcc4,0xbd35bd35,0xbcc43d6d,
0x3d0ebd55,0xbd7bbc48,0x3c483d7b,0x3d55bd0e,0xbd800000,0x3cc43d6d,0x3d35bd35,0xbd6dbcc4,0x3d553d0e,0x3c48bd7b,0xbd7b3c48,0x3d0e3d55,0x8000bd80,0xbd6d3cc4,0x3d353d35,0x3cc4bd6d,
0x80003d80,0x3d353d35,0x3d800000,0x3d35bd35,0xbcc4bd6d,0xbd6dbcc4,0xbd6d3cc4,0xbcc43d6d,0x8000bd80,0xbd35bd35,0xbd800000,0xbd353d35,0x3cc43d6d,0x3d6d3cc4,0x3d6dbcc4,0x3cc4bd6d,
0x80003d80,0x3d353d35,0x3d800000,0x3d35bd35,0xbcc4bd6d,0xbd6dbcc4,0xbd6d3cc4,0xbcc43d6d,0x8000bd80,0xbd35bd35,0xbd800000,0xbd353d35,0x3cc43d6d,0x3d6d3cc4,0x3d6dbcc4,0x3cc4bd6d,
0xbd6dbcc4,0x3cc43d6d,0x3cc4bd6d,0xbd6d3cc4,0x80003d80,0x3d35bd35,0xbd800000,0x3d353d35,0x3d6d3cc4,0xbcc4bd6d,0xbcc43d6d,0x3d6dbcc4,0x8000bd80,0xbd353d35,0x3d800000,0xbd35bd35,
0xbd6dbcc4,0x3cc43d6d,0x3cc4bd6d,0xbd6d3cc4,0x80003d80,0x3d35bd35,0xbd800000,0x3d353d35,0x3d6d3cc4,0xbcc4bd6d,0xbcc43d6d,0x3d6dbcc4,0x8000bd80,0xbd353d35,0x3d800000,0xbd35bd35,
0x3d800000,0x3cc4bd6d,0xbd35bd35,0xbd6d3cc4,0xbd553d0e,0x3c483d7b,0x3d7b3c48,0x3d0ebd55,0x8000bd80,0xbd6dbcc4,0xbd353d35,0x3cc43d6d,0x3d0e3d55,0x3d7bbc48,0x3c48bd7b,0xbd55bd0e,
0xbd800000,0xbcc43d6d,0x3d353d35,0x3d6dbcc4,0x3d55bd0e,0xbc48bd7b,0xbd7bbc48,0xbd0e3d55,0x80003d80,0x3d6d3cc4,0x3d35bd35,0xbcc4bd6d,0xbd0ebd55,0xbd7b3c48,0xbc483d7b,0x3d553d0e,
0xbc483d7b,0x3d0ebd55,0xbd553d0e,0x3d7bbc48,0x3d800000,0xbd6dbcc4,0x3d353d35,0xbcc4bd6d,0x3d7b3c48,0xbd55bd0e,0x3d0e3d55,0xbc48bd7b,0x8000bd80,0xbcc43d6d,0x3d35bd35,0xbd6d3cc4,
0x3c48bd7b,0xbd0e3d55,0x3d55bd0e,0xbd7b3c48,0xbd800000,0x3d6d3cc4,0xbd35bd35,0x3cc43d6d,0xbd7bbc48,0x3d553d0e,0xbd0ebd55,0x3c483d7b,0x80003d80,0x3cc4bd6d,0xbd353d35,0x3d6dbcc4,
0x3d800000,0x3d800000,0x3d800000,0x3d800000,0xbd800000,0xbd800000,0xbd800000,0xbd800000,0x3d800000,0x3d800000,0x3d800000,0x3d800000,0xbd800000,0xbd800000,0xbd800000,0xbd800000,
0x3d800000,0x3d800000,0x3d800000,0x3d800000,0xbd800000,0xbd800000,0xbd800000,0xbd800000,0x3d800000,0x3d800000,0x3d800000,0x3d800000,0xbd800000,0xbd800000,0xbd800000,0xbd800000,
0xbd353d35,0x3d353d35,0x3d35bd35,0xbd35bd35,0x3d800000,0xbd80,0xbd800000,0x3d80,0xbd353d35,0x3d353d35,0x3d35bd35,0xbd35bd35,0x3d800000,0xbd80,0xbd800000,0x3d80,
0xbd353d35,0x3d353d35,0x3d35bd35,0xbd35bd35,0x3d800000,0xbd80,0xbd800000,0x3d80,0xbd353d35,0x3d353d35,0x3d35bd35,0xbd35bd35,0x3d800000,0xbd80,0xbd800000,0x3d80,
0xbd80,0xbcc4bd6d,0xbd35bd35,0xbd6dbcc4,0x3c483d7b,0x3d0e3d55,0x3d553d0e,0x3d7b3c48,0x3d800000,0x3d6dbcc4,0x3d35bd35,0x3cc4bd6d,0xbd7b3c48,0xbd553d0e,0xbd0e3d55,0xbc483d7b,
0x3d80,0x3cc43d6d,0x3d353d35,0x3d6d3cc4,0xbc48bd7b,0xbd0ebd55,0xbd55bd0e,0xbd7bbc48,0xbd800000,0xbd6d3cc4,0xbd353d35,0xbcc43d6d,0x3d7bbc48,0x3d55bd0e,0x3d0ebd55,0x3c48bd7b,
0x3d553d0e,0x3c48bd7b,0xbd7b3c48,0x3d0e3d55,0xbd80,0xbd6d3cc4,0x3d353d35,0x3cc4bd6d,0xbd0e3d55,0x3d7b3c48,0xbc48bd7b,0xbd553d0e,0x3d800000,0xbcc4bd6d,0xbd353d35,0x3d6d3cc4,
0xbd55bd0e,0xbc483d7b,0x3d7bbc48,0xbd0ebd55,0x3d80,0x3d6dbcc4,0xbd35bd35,0xbcc43d6d,0x3d0ebd55,0xbd7bbc48,0x3c483d7b,0x3d55bd0e,0xbd800000,0x3cc43d6d,0x3d35bd35,0xbd6dbcc4,
0x3d800000,0x3d35bd35,0xbd80,0xbd35bd35,0xbd6d3cc4,0xbcc43d6d,0x3cc43d6d,0x3d6d3cc4,0xbd800000,0xbd353d35,0x3d80,0x3d353d35,0x3d6dbcc4,0x3cc4bd6d,0xbcc4bd6d,0xbd6dbcc4,
0x3d800000,0x3d35bd35,0xbd80,0xbd35bd35,0xbd6d3cc4,0xbcc43d6d,0x3cc43d6d,0x3d6d3cc4,0xbd800000,0xbd353d35,0x3d80,0x3d353d35,0x3d6dbcc4,0x3cc4bd6d,0xbcc4bd6d,0xbd6dbcc4,
0xbcc43d6d,0x3d6dbcc4,0xbd6dbcc4,0x3cc43d6d,0x3d800000,0xbd35bd35,0x3d80,0x3d35bd35,0x3cc4bd6d,0xbd6d3cc4,0x3d6d3cc4,0xbcc4bd6d,0xbd800000,0x3d353d35,0xbd80,0xbd353d35,
0xbcc43d6d,0x3d6dbcc4,0xbd6dbcc4,0x3cc43d6d,0x3d800000,0xbd35bd35,0x3d80,0x3d35bd35,0x3cc4bd6d,0xbd6d3cc4,0x3d6d3cc4,0xbcc4bd6d,0xbd800000,0x3d353d35,0xbd80,0xbd353d35,
0xbd80,0xbd6dbcc4,0xbd353d35,0x3cc43d6d,0x3d0e3d55,0x3d7bbc48,0x3c48bd7b,0xbd55bd0e,0xbd800000,0xbcc43d6d,0x3d353d35,0x3d6dbcc4,0x3d55bd0e,0xbc48bd7b,0xbd7bbc48,0xbd0e3d55,
0x3d80,0x3d6d3cc4,0x3d35bd35,0xbcc4bd6d,0xbd0ebd55,0xbd7b3c48,0xbc483d7b,0x3d553d0e,0x3d800000,0x3cc4bd6d,0xbd35bd35,0xbd6d3cc4,0xbd553d0e,0x3c483d7b,0x3d7b3c48,0x3d0ebd55,
0x3d7b3c48,0xbd55bd0e,0x3d0e3d55,0xbc48bd7b,0xbd80,0xbcc43d6d,0x3d35bd35,0xbd6d3cc4,0x3c48bd7b,0xbd0e3d55,0x3d55bd0e,0xbd7b3c48,0xbd800000,0x3d6d3cc4,0xbd35bd35,0x3cc43d6d,
0xbd7bbc48,0x3d553d0e,0xbd0ebd55,0x3c483d7b,0x3d80,0x3cc4bd6d,0xbd353d35,0x3d6dbcc4,0xbc483d7b,0x3d0ebd55,0xbd553d0e,0x3d7bbc48,0x3d800000,0xbd6dbcc4,0x3d353d35,0xbcc4bd6d,
0x80003d80,0x8000bd80,0x80003d80,0x8000bd80,0xbd800000,0x3d800000,0xbd800000,0x3d800000,0x80003d80,0x8000bd80,0x80003d80,0x8000bd80,0xbd800000,0x3d800000,0xbd800000,0x3d800000,
0x80003d80,0x8000bd80,0x80003d80,0x8000bd80,0xbd800000,0x3d800000,0xbd800000,0x3d800000,0x80003d80,0x8000bd80,0x80003d80,0x8000bd80,0xbd800000,0x3d800000,0xbd800000,0x3d800000,
0xbd353d35,0xbd35bd35,0x3d35bd35,0x3d353d35,0x80003d80,0xbd800000,0x8000bd80,0x3d800000,0xbd353d35,0xbd35bd35,0x3d35bd35,0x3d353d35,0x80003d80,0xbd800000,0x8000bd80,0x3d800000,
0xbd353d35,0xbd35bd35,0x3d35bd35,0x3d353d35,0x80003d80,0xbd800000,0x8000bd80,0x3d800000,0xbd353d35,0xbd35bd35,0x3d35bd35,0x3d353d35,0x80003d80,0xbd800000,0x8000bd80,0x3d800000,
0x3d800000,0xbd6d3cc4,0x3d35bd35,0xbcc43d6d,0x3c483d7b,0xbd0ebd55,0x3d553d0e,0xbd7bbc48,0x80003d80,0xbcc4bd6d,0x3d353d35,0xbd6dbcc4,0xbd7b3c48,0x3d55bd0e,0xbd0e3d55,0x3c48bd7b,
0xbd800000,0x3d6dbcc4,0xbd353d35,0x3cc4bd6d,0xbc48bd7b,0x3d0e3d55,0xbd55bd0e,0x3d7b3c48,0x8000bd80,0x3cc43d6d,0xbd35bd35,0x3d6d3cc4,0x3d7bbc48,0xbd553d0e,0x3d0ebd55,0xbc483d7b,
0x3d553d0e,0xbc483d7b,0xbd7b3c48,0xbd0ebd55,0x3d800000,0x3cc43d6d,0xbd353d35,0xbd6dbcc4,0xbd0e3d55,0xbd7bbc48,0xbc48bd7b,0x3d55bd0e,0x80003d80,0xbd6d3cc4,0xbd35bd35,0x3cc4bd6d,
0xbd55bd0e,0x3c48bd7b,0x3d7bbc48,0x3d0e3d55,0xbd800000,0xbcc4bd6d,0x3d35bd35,0x3d6d3cc4,0x3d0ebd55,0x3d7b3c48,0x3c483d7b,0xbd553d0e,0x8000bd80,0x3d6dbcc4,0x3d353d35,0xbcc43d6d,
0x80003d80,0xbd35bd35,0x3d800000,0xbd353d35,0xbd6d3cc4,0x3cc4bd6d,0x3cc43d6d,0xbd6dbcc4,0x8000bd80,0x3d353d35,0xbd800000,0x3d35bd35,0x3d6dbcc4,0xbcc43d6d,0xbcc4bd6d,0x3d6d3cc4,
0x80003d80,0xbd35bd35,0x3d800000,0xbd353d35,0xbd6d3cc4,0x3cc4bd6d,0x3cc43d6d,0xbd6dbcc4,0x8000bd80,0x3d353d35,0xbd800000,0x3d35bd35,0x3d6dbcc4,0xbcc43d6d,0xbcc4bd6d,0x3d6d3cc4,
0xbcc43d6d,0xbd6d3cc4,0xbd6dbcc4,0xbcc4bd6d,0x80003d80,0xbd353d35,0xbd800000,0xbd35bd35,0x3cc4bd6d,0x3d6dbcc4,0x3d6d3cc4,0x3cc43d6d,0x8000bd80,0x3d35bd35,0x3d800000,0x3d353d35,
0xbcc43d6d,0xbd6d3cc4,0xbd6dbcc4,0xbcc4bd6d,0x80003d80,0xbd353d35,0xbd800000,0xbd35bd35,0x3cc4bd6d,0x3d6dbcc4,0x3d6d3cc4,0x3cc43d6d,0x8000bd80,0x3d35bd35,0x3d800000,0x3d353d35,
0x3d800000,0xbcc43d6d,0xbd35bd35,0x3d6dbcc4,0x3d0e3d55,0xbd7b3c48,0x3c48bd7b,0x3d553d0e,0x8000bd80,0x3d6d3cc4,0xbd353d35,0xbcc4bd6d,0x3d55bd0e,0x3c483d7b,0xbd7bbc48,0x3d0ebd55,
0xbd800000,0x3cc4bd6d,0x3d353d35,0xbd6d3cc4,0xbd0ebd55,0x3d7bbc48,0xbc483d7b,0xbd55bd0e,0x80003d80,0xbd6dbcc4,0x3d35bd35,0x3cc43d6d,0xbd553d0e,0xbc48bd7b,0x3d7b3c48,0xbd0e3d55,
0x3d7b3c48,0x3d553d0e,0x3d0e3d55,0x3c483d7b,0x3d800000,0x3d6d3cc4,0x3d353d35,0x3cc43d6d,0x3c48bd7b,0x3d0ebd55,0x3d55bd0e,0x3d7bbc48,0x8000bd80,0x3cc4bd6d,0x3d35bd35,0x3d6dbcc4,
0xbd7bbc48,0xbd55bd0e,0xbd0ebd55,0xbc48bd7b,0xbd800000,0xbd6dbcc4,0xbd35bd35,0xbcc4bd6d,0xbc483d7b,0xbd0e3d55,0xbd553d0e,0xbd7b3c48,0x80003d80,0xbcc43d6d,0xbd353d35,0xbd6d3cc4,
0x3d800000,0xbd800000,0x3d800000,0xbd800000,0x3d80,0xbd80,0x3d80,0xbd80,0x3d800000,0xbd800000,0x3d800000,0xbd800000,0x3d80,0xbd80,0x3d80,0xbd80,
0x3d800000,0xbd800000,0x3d800000,0xbd800000,0x3d80,0xbd80,0x3d80,0xbd80,0x3d800000,0xbd800000,0x3d800000,0xbd800000,0x3d80,0xbd80,0x3d80,0xbd80,
0x3d353d35,0xbd353d35,0xbd35bd35,0x3d35bd35,0x3d800000,0x3d80,0xbd800000,0xbd80,0x3d353d35,0xbd353d35,0xbd35bd35,0x3d35bd35,0x3d800000,0x3d80,0xbd800000,0xbd80,
0x3d353d35,0xbd353d35,0xbd35bd35,0x3d35bd35,0x3d800000,0x3d80,0xbd800000,0xbd80,0x3d353d35,0xbd353d35,0xbd35bd35,0x3d35bd35,0x3d800000,0x3d80,0xbd800000,0xbd80,
0xbd80,0x3cc43d6d,0xbd35bd35,0x3d6d3cc4,0x3d7bbc48,0xbd553d0e,0x3d0ebd55,0xbc483d7b,0x3d800000,0xbd6d3cc4,0x3d35bd35,0xbcc43d6d,0x3c483d7b,0xbd0ebd55,0x3d553d0e,0xbd7bbc48,
0x3d80,0xbcc4bd6d,0x3d353d35,0xbd6dbcc4,0xbd7b3c48,0x3d55bd0e,0xbd0e3d55,0x3c48bd7b,0xbd800000,0x3d6dbcc4,0xbd353d35,0x3cc4bd6d,0xbc48bd7b,0x3d0e3d55,0xbd55bd0e,0x3d7b3c48,
0x3d0ebd55,0x3d7b3c48,0x3c483d7b,0xbd553d0e,0xbd80,0x3d6dbcc4,0x3d353d35,0xbcc43d6d,0x3d553d0e,0xbc483d7b,0xbd7b3c48,0xbd0ebd55,0x3d800000,0x3cc43d6d,0xbd353d35,0xbd6dbcc4,
0xbd0e3d55,0xbd7bbc48,0xbc48bd7b,0x3d55bd0e,0x3d80,0xbd6d3cc4,0xbd35bd35,0x3cc4bd6d,0xbd55bd0e,0x3c48bd7b,0x3d7bbc48,0x3d0e3d55,0xbd800000,0xbcc4bd6d,0x3d35bd35,0x3d6d3cc4,
0x3d800000,0xbd353d35,0xbd80,0x3d353d35,0x3cc43d6d,0xbd6dbcc4,0x3d6dbcc4,0xbcc43d6d,0xbd800000,0x3d35bd35,0x3d80,0xbd35bd35,0xbcc4bd6d,0x3d6d3cc4,0xbd6d3cc4,0x3cc4bd6d,
0x3d800000,0xbd353d35,0xbd80,0x3d353d35,0x3cc43d6d,0xbd6dbcc4,0x3d6dbcc4,0xbcc43d6d,0xbd800000,0x3d35bd35,0x3d80,0xbd35bd35,0xbcc4bd6d,0x3d6d3cc4,0xbd6d3cc4,0x3cc4bd6d,
0x3d6d3cc4,0x3cc43d6d,0xbcc43d6d,0xbd6d3cc4,0x3d800000,0x3d353d35,0x3d80,0xbd353d35,0xbd6dbcc4,0xbcc4bd6d,0x3cc4bd6d,0x3d6dbcc4,0xbd800000,0xbd35bd35,0xbd80,0x3d35bd35,
0x3d6d3cc4,0x3cc43d6d,0xbcc43d6d,0xbd6d3cc4,0x3d800000,0x3d353d35,0x3d80,0xbd353d35,0xbd6dbcc4,0xbcc4bd6d,0x3cc4bd6d,0x3d6dbcc4,0xbd800000,0xbd35bd35,0xbd80,0x3d35bd35,
0xbd80,0x3d6d3cc4,0xbd353d35,0xbcc4bd6d,0x3d55bd0e,0x3c483d7b,0xbd7bbc48,0x3d0ebd55,0xbd800000,0x3cc4bd6d,0x3d353d35,0xbd6d3cc4,0xbd0ebd55,0x3d7bbc48,0xbc483d7b,0xbd55bd0e,
0x3d80,0xbd6dbcc4,0x3d35bd35,0x3cc43d6d,0xbd553d0e,0xbc48bd7b,0x3d7b3c48,0xbd0e3d55,0x3d800000,0xbcc43d6d,0xbd35bd35,0x3d6dbcc4,0x3d0e3d55,0xbd7b3c48,0x3c48bd7b,0x3d553d0e,
0x3c48bd7b,0x3d0ebd55,0x3d55bd0e,0x3d7bbc48,0xbd80,0x3cc4bd6d,0x3d35bd35,0x3d6dbcc4,0xbd7bbc48,0xbd55bd0e,0xbd0ebd55,0xbc48bd7b,0xbd800000,0xbd6dbcc4,0xbd35bd35,0xbcc4bd6d,
0xbc483d7b,0xbd0e3d55,0xbd553d0e,0xbd7b3c48,0x3d80,0xbcc43d6d,0xbd353d35,0xbd6d3cc4,0x3d7b3c48,0x3d553d0e,0x3d0e3d55,0x3c483d7b,0x3d800000,0x3d6d3cc4,0x3d353d35,0x3cc43d6d,
0x3d80,0x3d80,0x3d80,0x3d80,0x3d80,0x3d80,0x3d80,0x3d80,0x3d80,0x3d80,0x3d80,0x3d80,0x3d80,0x3d80,0x3d80,0x3d80,
0x3d80,0x3d80,0x3d80,0x3d80,0x3d80,0x3d80,0x3d80,0x3d80,0x3d80,0x3d80,0x3d80,0x3d80,0x3d80,0x3d80,0x3d80,0x3d80,
0xbd353d35,0xbd553d0e,0xbd6d3cc4,0xbd7b3c48,0x3d80,0xbc483d7b,0xbcc43d6d,0xbd0e3d55,0xbd35bd35,0xbd0ebd55,0xbcc4bd6d,0xbc48bd7b,0xbd800000,0xbd7bbc48,0xbd6dbcc4,0xbd55bd0e,
0x3d35bd35,0x3d55bd0e,0x3d6dbcc4,0x3d7bbc48,0xbd80,0x3c48bd7b,0x3cc4bd6d,0x3d0ebd55,0x3d353d35,0x3d0e3d55,0x3cc43d6d,0x3c483d7b,0x3d800000,0x3d7b3c48,0x3d6d3cc4,0x3d553d0e,
0xbd80,0x3cc4bd6d,0x3d35bd35,0x3d6dbcc4,0x3d800000,0x3d6d3cc4,0x3d353d35,0x3cc43d6d,0x3d80,0xbcc43d6d,0xbd353d35,0xbd6d3cc4,0xbd800000,0xbd6dbcc4,0xbd35bd35,0xbcc4bd6d,
0xbd80,0x3cc4bd6d,0x3d35bd35,0x3d6dbcc4,0x3d800000,0x3d6d3cc4,0x3d353d35,0x3cc43d6d,0x3d80,0xbcc43d6d,0xbd353d35,0xbd6d3cc4,0xbd800000,0xbd6dbcc4,0xbd35bd35,0xbcc4bd6d,
0xbd353d35,0xbd7b3c48,0xbd6dbcc4,0xbd0ebd55,0x3d800000,0x3d553d0e,0x3cc43d6d,0xbc483d7b,0xbd35bd35,0xbc48bd7b,0x3cc4bd6d,0x3d55bd0e,0x3d80,0xbd0e3d55,0xbd6d3cc4,0xbd7bbc48,
0x3d35bd35,0x3d7bbc48,0x3d6d3cc4,0x3d0e3d55,0xbd800000,0xbd55bd0e,0xbcc4bd6d,0x3c48bd7b,0x3d353d35,0x3c483d7b,0xbcc43d6d,0xbd553d0e,0xbd80,0x3d0ebd55,0x3d6dbcc4,0x3d7b3c48,
0x3d80,0xbd353d35,0xbd800000,0xbd35bd35,0xbd80,0x3d35bd35,0x3d800000,0x3d353d35,0x3d80,0xbd353d35,0xbd800000,0xbd35bd35,0xbd80,0x3d35bd35,0x3d800000,0x3d353d35,
0x3d80,0xbd353d35,0xbd800000,0xbd35bd35,0xbd80,0x3d35bd35,0x3d800000,0x3d353d35,0x3d80,0xbd353d35,0xbd800000,0xbd35bd35,0xbd80,0x3d35bd35,0x3d800000,0x3d353d35,
0xbd353d35,0xbd7bbc48,0xbcc4bd6d,0x3d0ebd55,0xbd80,0x3d55bd0e,0x3d6d3cc4,0x3c483d7b,0xbd35bd35,0x3c48bd7b,0x3d6dbcc4,0x3d553d0e,0x3d800000,0x3d0e3d55,0xbcc43d6d,0xbd7b3c48,
0x3d35bd35,0x3d7b3c48,0x3cc43d6d,0xbd0e3d55,0x3d80,0xbd553d0e,0xbd6dbcc4,0xbc48bd7b,0x3d353d35,0xbc483d7b,0xbd6d3cc4,0xbd55bd0e,0xbd800000,0xbd0ebd55,0x3cc4bd6d,0x3d7bbc48,
0xbd80,0x3d6dbcc4,0x3d353d35,0xbcc43d6d,0xbd800000,0xbcc4bd6d,0x3d35bd35,0x3d6d3cc4,0x3d80,0xbd6d3cc4,0xbd35bd35,0x3cc4bd6d,0x3d800000,0x3cc43d6d,0xbd353d35,0xbd6dbcc4,
0xbd80,0x3d6dbcc4,0x3d353d35,0xbcc43d6d,0xbd800000,0xbcc4bd6d,0x3d35bd35,0x3d6d3cc4,0x3d80,0xbd6d3cc4,0xbd35bd35,0x3cc4bd6d,0x3d800000,0x3cc43d6d,0xbd353d35,0xbd6dbcc4,
0xbd353d35,0xbd55bd0e,0x3cc4bd6d,0x3d7b3c48,0xbd800000,0xbc48bd7b,0x3d6dbcc4,0x3d0e3d55,0xbd35bd35,0x3d0ebd55,0x3d6d3cc4,0xbc483d7b,0xbd80,0x3d7bbc48,0x3cc43d6d,0xbd553d0e,
0x3d35bd35,0x3d553d0e,0xbcc43d6d,0xbd7bbc48,0x3d800000,0x3c483d7b,0xbd6d3cc4,0xbd0ebd55,0x3d353d35,0xbd0e3d55,0xbd6dbcc4,0x3c48bd7b,0x3d80,0xbd7b3c48,0xbcc4bd6d,0x3d55bd0e,
0xbd800000,0xbd800000,0xbd800000,0xbd800000,0xbd800000,0xbd800000,0xbd800000,0xbd800000,0xbd800000,0xbd800000,0xbd800000,0xbd800000,0xbd800000,0xbd800000,0xbd800000,0xbd800000,
0xbd800000,0xbd800000,0xbd800000,0xbd800000,0xbd800000,0xbd800000,0xbd800000,0xbd800000,0xbd800000,0xbd800000,0xbd800000,0xbd800000,0xbd800000,0xbd800000,0xbd800000,0xbd800000,
0xbd35bd35,0xbd0ebd55,0xbcc4bd6d,0xbc48bd7b,0xbd800000,0xbd7bbc48,0xbd6dbcc4,0xbd55bd0e,0x3d35bd35,0x3d55bd0e,0x3d6dbcc4,0x3d7bbc48,0x8000bd80,0x3c48bd7b,0x3cc4bd6d,0x3d0ebd55,
0x3d353d35,0x3d0e3d55,0x3cc43d6d,0x3c483d7b,0x3d800000,0x3d7b3c48,0x3d6d3cc4,0x3d553d0e,0xbd353d35,0xbd553d0e,0xbd6d3cc4,0xbd7b3c48,0x80003d80,0xbc483d7b,0xbcc43d6d,0xbd0e3d55,
0x3d800000,0x3d6d3cc4,0x3d353d35,0x3cc43d6d,0x80003d80,0xbcc43d6d,0xbd353d35,0xbd6d3cc4,0xbd800000,0xbd6dbcc4,0xbd35bd35,0xbcc4bd6d,0x8000bd80,0x3cc4bd6d,0x3d35bd35,0x3d6dbcc4,
0x3d800000,0x3d6d3cc4,0x3d353d35,0x3cc43d6d,0x80003d80,0xbcc43d6d,0xbd353d35,0xbd6d3cc4,0xbd800000,0xbd6dbcc4,0xbd35bd35,0xbcc4bd6d,0x8000bd80,0x3cc4bd6d,0x3d35bd35,0x3d6dbcc4,
0xbd35bd35,0xbc48bd7b,0x3cc4bd6d,0x3d55bd0e,0x80003d80,0xbd0e3d55,0xbd6d3cc4,0xbd7bbc48,0x3d35bd35,0x3d7bbc48,0x3d6d3cc4,0x3d0e3d55,0xbd800000,0xbd55bd0e,0xbcc4bd6d,0x3c48bd7b,
0x3d353d35,0x3c483d7b,0xbcc43d6d,0xbd553d0e,0x8000bd80,0x3d0ebd55,0x3d6dbcc4,0x3d7b3c48,0xbd353d35,0xbd7b3c48,0xbd6dbcc4,0xbd0ebd55,0x3d800000,0x3d553d0e,0x3cc43d6d,0xbc483d7b,
0xbd800000,0xbd35bd35,0x8000bd80,0x3d35bd35,0x3d800000,0x3d353d35,0x80003d80,0xbd353d35,0xbd800000,0xbd35bd35,0x8000bd80,0x3d35bd35,0x3d800000,0x3d353d35,0x80003d80,0xbd353d35,
0xbd800000,0xbd35bd35,0x8000bd80,0x3d35bd35,0x3d800000,0x3d353d35,0x80003d80,0xbd353d35,0xbd800000,0xbd35bd35,0x8000bd80,0x3d35bd35,0x3d800000,0x3d353d35,0x80003d80,0xbd353d35,
0xbd35bd35,0x3c48bd7b,0x3d6dbcc4,0x3d553d0e,0x3d800000,0x3d0e3d55,0xbcc43d6d,0xbd7b3c48,0x3d35bd35,0x3d7b3c48,0x3cc43d6d,0xbd0e3d55,0x80003d80,0xbd553d0e,0xbd6dbcc4,0xbc48bd7b,
0x3d353d35,0xbc483d7b,0xbd6d3cc4,0xbd55bd0e,0xbd800000,0xbd0ebd55,0x3cc4bd6d,0x3d7bbc48,0xbd353d35,0xbd7bbc48,0xbcc4bd6d,0x3d0ebd55,0x8000bd80,0x3d55bd0e,0x3d6d3cc4,0x3c483d7b,
0x3d800000,0x3cc43d6d,0xbd353d35,0xbd6dbcc4,0x8000bd80,0x3d6dbcc4,0x3d353d35,0xbcc43d6d,0xbd800000,0xbcc4bd6d,0x3d35bd35,0x3d6d3cc4,0x80003d80,0xbd6d3cc4,0xbd35bd35,0x3cc4bd6d,
0x3d800000,0x3cc43d6d,0xbd353d35,0xbd6dbcc4,0x8000bd80,0x3d6dbcc4,0x3d353d35,0xbcc43d6d,0xbd800000,0xbcc4bd6d,0x3d35bd35,0x3d6d3cc4,0x80003d80,0xbd6d3cc4,0xbd35bd35,0x3cc4bd6d,
0xbd35bd35,0x3d0ebd55,0x3d6d3cc4,0xbc483d7b,0x8000bd80,0x3d7bbc48,0x3cc43d6d,0xbd553d0e,0x3d35bd35,0x3d553d0e,0xbcc43d6d,0xbd7bbc48,0x3d800000,0x3c483d7b,0xbd6d3cc4,0xbd0ebd55,
0x3d353d35,0xbd0e3d55,0xbd6dbcc4,0x3c48bd7b,0x80003d80,0xbd7b3c48,0xbcc4bd6d,0x3d55bd0e,0xbd353d35,0xbd55bd0e,0x3cc4bd6d,0x3d7b3c48,0xbd800000,0xbc48bd7b,0x3d6dbcc4,0x3d0e3d55,
0x3d80,0xbd800000,0xbd80,0x3d800000,0x3d80,0xbd800000,0xbd80,0x3d800000,0x3d80,0xbd800000,0xbd80,0x3d800000,0x3d80,0xbd800000,0xbd80,0x3d800000,
0x3d80,0xbd800000,0xbd80,0x3d800000,0x3d80,0xbd800000,0xbd80,0x3d800000,0x3d80,0xbd800000,0xbd80,0x3d800000,0x3d80,0xbd800000,0xbd80,0x3d800000,
0xbd353d35,0xbd0ebd55,0x3d6dbcc4,0x3c483d7b,0x3d80,0xbd7bbc48,0x3cc4bd6d,0x3d553d0e,0xbd35bd35,0x3d55bd0e,0x3cc43d6d,0xbd7b3c48,0xbd800000,0x3c48bd7b,0x3d6d3cc4,0xbd0e3d55,
0x3d35bd35,0x3d0e3d55,0xbd6d3cc4,0xbc48bd7b,0xbd80,0x3d7b3c48,0xbcc43d6d,0xbd55bd0e,0x3d353d35,0xbd553d0e,0xbcc4bd6d,0x3d7bbc48,0x3d800000,0xbc483d7b,0xbd6dbcc4,0x3d0ebd55,
0xbd80,0x3d6d3cc4,0xbd353d35,0xbcc4bd6d,0x3d800000,0xbcc43d6d,0xbd35bd35,0x3d6dbcc4,0x3d80,0xbd6dbcc4,0x3d35bd35,0x3cc43d6d,0xbd800000,0x3cc4bd6d,0x3d353d35,0xbd6d3cc4,
0xbd80,0x3d6d3cc4,0xbd353d35,0xbcc4bd6d,0x3d800000,0xbcc43d6d,0xbd35bd35,0x3d6dbcc4,0x3d80,0xbd6dbcc4,0x3d35bd35,0x3cc43d6d,0xbd800000,0x3cc4bd6d,0x3d353d35,0xbd6d3cc4,
0xbd353d35,0xbc48bd7b,0x3d6d3cc4,0xbd553d0e,0x3d800000,0xbd0e3d55,0xbcc4bd6d,0x3d7b3c48,0xbd35bd35,0x3d7bbc48,0xbcc43d6d,0xbd0ebd55,0x3d80,0xbd55bd0e,0x3d6dbcc4,0xbc483d7b,
0x3d35bd35,0x3c483d7b,0xbd6dbcc4,0x3d55bd0e,0xbd800000,0x3d0ebd55,0x3cc43d6d,0xbd7bbc48,0x3d353d35,0xbd7b3c48,0x3cc4bd6d,0x3d0e3d55,0xbd80,0x3d553d0e,0xbd6d3cc4,0x3c48bd7b,
0x3d80,0xbd35bd35,0x3d800000,0xbd353d35,0xbd80,0x3d353d35,0xbd800000,0x3d35bd35,0x3d80,0xbd35bd35,0x3d800000,0xbd353d35,0xbd80,0x3d353d35,0xbd800000,0x3d35bd35,
0x3d80,0xbd35bd35,0x3d800000,0xbd353d35,0xbd80,0x3d353d35,0xbd800000,0x3d35bd35,0x3d80,0xbd35bd35,0x3d800000,0xbd353d35,0xbd80,0x3d353d35,0xbd800000,0x3d35bd35,
0xbd353d35,0x3c48bd7b,0x3cc43d6d,0xbd55bd0e,0xbd80,0x3d0e3d55,0xbd6dbcc4,0x3d7bbc48,0xbd35bd35,0x3d7b3c48,0xbd6d3cc4,0x3d0ebd55,0x3d800000,0xbd553d0e,0x3cc4bd6d,0x3c483d7b,
0x3d35bd35,0xbc483d7b,0xbcc4bd6d,0x3d553d0e,0x3d80,0xbd0ebd55,0x3d6d3cc4,0xbd7b3c48,0x3d353d35,0xbd7bbc48,0x3d6dbcc4,0xbd0e3d55,0xbd800000,0x3d55bd0e,0xbcc43d6d,0xbc48bd7b,
0xbd80,0x3cc43d6d,0xbd35bd35,0x3d6d3cc4,0xbd800000,0x3d6dbcc4,0xbd353d35,0x3cc4bd6d,0x3d80,0xbcc4bd6d,0x3d353d35,0xbd6dbcc4,0x3d800000,0xbd6d3cc4,0x3d35bd35,0xbcc43d6d,
0xbd80,0x3cc43d6d,0xbd35bd35,0x3d6d3cc4,0xbd800000,0x3d6dbcc4,0xbd353d35,0x3cc4bd6d,0x3d80,0xbcc4bd6d,0x3d353d35,0xbd6dbcc4,0x3d800000,0xbd6d3cc4,0x3d35bd35,0xbcc43d6d,
0xbd353d35,0x3d0ebd55,0xbcc43d6d,0x3c48bd7b,0xbd800000,0x3d7bbc48,0xbd6d3cc4,0x3d55bd0e,0xbd35bd35,0x3d553d0e,0xbd6dbcc4,0x3d7b3c48,0xbd80,0x3c483d7b,0xbcc4bd6d,0x3d0e3d55,
0x3d35bd35,0xbd0e3d55,0x3cc4bd6d,0xbc483d7b,0x3d800000,0xbd7b3c48,0x3d6dbcc4,0xbd553d0e,0x3d353d35,0xbd55bd0e,0x3d6d3cc4,0xbd7bbc48,0x3d80,0xbc48bd7b,0x3cc43d6d,0xbd0ebd55,
0xbd800000,0x8000bd80,0x3d800000,0x80003d80,0xbd800000,0x8000bd80,0x3d800000,0x80003d80,0xbd800000,0x8000bd80,0x3d800000,0x80003d80,0xbd800000,0x8000bd80,0x3d800000,0x80003d80,
0xbd800000,0x8000bd80,0x3d800000,0x80003d80,0xbd800000,0x8000bd80,0x3d800000,0x80003d80,0xbd800000,0x8000bd80,0x3d800000,0x80003d80,0xbd800000,0x8000bd80,0x3d800000,0x80003d80,
0xbd35bd35,0x3d55bd0e,0x3cc43d6d,0xbd7b3c48,0xbd800000,0x3c48bd7b,0x3d6d3cc4,0xbd0e3d55,0x3d35bd35,0x3d0e3d55,0xbd6d3cc4,0xbc48bd7b,0x8000bd80,0x3d7b3c48,0xbcc43d6d,0xbd55bd0e,
0x3d353d35,0xbd553d0e,0xbcc4bd6d,0x3d7bbc48,0x3d800000,0xbc483d7b,0xbd6dbcc4,0x3d0ebd55,0xbd353d35,0xbd0ebd55,0x3d6dbcc4,0x3c483d7b,0x80003d80,0xbd7bbc48,0x3cc4bd6d,0x3d553d0e,
0x3d800000,0xbcc43d6d,0xbd35bd35,0x3d6dbcc4,0x80003d80,0xbd6dbcc4,0x3d35bd35,0x3cc43d6d,0xbd800000,0x3cc4bd6d,0x3d353d35,0xbd6d3cc4,0x8000bd80,0x3d6d3cc4,0xbd353d35,0xbcc4bd6d,
0x3d800000,0xbcc43d6d,0xbd35bd35,0x3d6dbcc4,0x80003d80,0xbd6dbcc4,0x3d35bd35,0x3cc43d6d,0xbd800000,0x3cc4bd6d,0x3d353d35,0xbd6d3cc4,0x8000bd80,0x3d6d3cc4,0xbd353d35,0xbcc4bd6d,
0xbd35bd35,0x3d7bbc48,0xbcc43d6d,0xbd0ebd55,0x80003d80,0xbd55bd0e,0x3d6dbcc4,0xbc483d7b,0x3d35bd35,0x3c483d7b,0xbd6dbcc4,0x3d55bd0e,0xbd800000,0x3d0ebd55,0x3cc43d6d,0xbd7bbc48,
0x3d353d35,0xbd7b3c48,0x3cc4bd6d,0x3d0e3d55,0x8000bd80,0x3d553d0e,0xbd6d3cc4,0x3c48bd7b,0xbd353d35,0xbc48bd7b,0x3d6d3cc4,0xbd553d0e,0x3d800000,0xbd0e3d55,0xbcc4bd6d,0x3d7b3c48,
0xbd800000,0x3d35bd35,0x80003d80,0xbd35bd35,0x3d800000,0xbd353d35,0x8000bd80,0x3d353d35,0xbd800000,0x3d35bd35,0x80003d80,0xbd35bd35,0x3d800000,0xbd353d35,0x8000bd80,0x3d353d35,
0xbd800000,0x3d35bd35,0x80003d80,0xbd35bd35,0x3d800000,0xbd353d35,0x8000bd80,0x3d353d35,0xbd800000,0x3d35bd35,0x80003d80,0xbd35bd35,0x3d800000,0xbd353d35,0x8000bd80,0x3d353d35,
0xbd35bd35,0x3d7b3c48,0xbd6d3cc4,0x3d0ebd55,0x3d800000,0xbd553d0e,0x3cc4bd6d,0x3c483d7b,0x3d35bd35,0xbc483d7b,0xbcc4bd6d,0x3d553d0e,0x80003d80,0xbd0ebd55,0x3d6d3cc4,0xbd7b3c48,
0x3d353d35,0xbd7bbc48,0x3d6dbcc4,0xbd0e3d55,0xbd800000,0x3d55bd0e,0xbcc43d6d,0xbc48bd7b,0xbd353d35,0x3c48bd7b,0x3cc43d6d,0xbd55bd0e,0x8000bd80,0x3d0e3d55,0xbd6dbcc4,0x3d7bbc48,
0x3d800000,0xbd6d3cc4,0x3d35bd35,0xbcc43d6d,0x8000bd80,0x3cc43d6d,0xbd35bd35,0x3d6d3cc4,0xbd800000,0x3d6dbcc4,0xbd353d35,0x3cc4bd6d,0x80003d80,0xbcc4bd6d,0x3d353d35,0xbd6dbcc4,
0x3d800000,0xbd6d3cc4,0x3d35bd35,0xbcc43d6d,0x8000bd80,0x3cc43d6d,0xbd35bd35,0x3d6d3cc4,0xbd800000,0x3d6dbcc4,0xbd353d35,0x3cc4bd6d,0x80003d80,0xbcc4bd6d,0x3d353d35,0xbd6dbcc4,
0xbd35bd35,0x3d553d0e,0xbd6dbcc4,0x3d7b3c48,0x8000bd80,0x3c483d7b,0xbcc4bd6d,0x3d0e3d55,0x3d35bd35,0xbd0e3d55,0x3cc4bd6d,0xbc483d7b,0x3d800000,0xbd7b3c48,0x3d6dbcc4,0xbd553d0e,
0x3d353d35,0xbd55bd0e,0x3d6d3cc4,0xbd7bbc48,0x80003d80,0xbc48bd7b,0x3cc43d6d,0xbd0ebd55,0xbd353d35,0x3d0ebd55,0xbcc43d6d,0x3c48bd7b,0xbd800000,0x3d7bbc48,0xbd6d3cc4,0x3d55bd0e,
0x3d80,0xbd80,0x3d80,0xbd80,0x3d80,0xbd80,0x3d80,0xbd80,0x3d80,0xbd80,0x3d80,0xbd80,0x3d80,0xbd80,0x3d80,0xbd80,
0x3d80,0xbd80,0x3d80,0xbd80,0x3d80,0xbd80,0x3d80,0xbd80,0x3d80,0xbd80,0x3d80,0xbd80,0x3d80,0xbd80,0x3d80,0xbd80,
0xbd353d35,0x3d55bd0e,0xbd6d3cc4,0x3d7bbc48,0x3d80,0x3c48bd7b,0xbcc43d6d,0x3d0ebd55,0xbd35bd35,0x3d0e3d55,0xbcc4bd6d,0x3c483d7b,0xbd800000,0x3d7b3c48,0xbd6dbcc4,0x3d553d0e,
0x3d35bd35,0xbd553d0e,0x3d6dbcc4,0xbd7b3c48,0xbd80,0xbc483d7b,0x3cc4bd6d,0xbd0e3d55,0x3d353d35,0xbd0ebd55,0x3cc43d6d,0xbc48bd7b,0x3d800000,0xbd7bbc48,0x3d6d3cc4,0xbd55bd0e,
0xbd80,0xbcc43d6d,0x3d35bd35,0xbd6d3cc4,0x3d800000,0xbd6dbcc4,0x3d353d35,0xbcc4bd6d,0x3d80,0x3cc4bd6d,0xbd353d35,0x3d6dbcc4,0xbd800000,0x3d6d3cc4,0xbd35bd35,0x3cc43d6d,
0xbd80,0xbcc43d6d,0x3d35bd35,0xbd6d3cc4,0x3d800000,0xbd6dbcc4,0x3d353d35,0xbcc4bd6d,0x3d80,0x3cc4bd6d,0xbd353d35,0x3d6dbcc4,0xbd800000,0x3d6d3cc4,0xbd35bd35,0x3cc43d6d,
0xbd353d35,0x3d7bbc48,0xbd6dbcc4,0x3d0e3d55,0x3d800000,0xbd55bd0e,0x3cc43d6d,0x3c48bd7b,0xbd35bd35,0x3c483d7b,0x3cc4bd6d,0xbd553d0e,0x3d80,0x3d0ebd55,0xbd6d3cc4,0x3d7b3c48,
0x3d35bd35,0xbd7b3c48,0x3d6d3cc4,0xbd0ebd55,0xbd800000,0x3d553d0e,0xbcc4bd6d,0xbc483d7b,0x3d353d35,0xbc48bd7b,0xbcc43d6d,0x3d55bd0e,0xbd80,0xbd0e3d55,0x3d6dbcc4,0xbd7bbc48,
0x3d80,0x3d35bd35,0xbd800000,0x3d353d35,0xbd80,0xbd353d35,0x3d800000,0xbd35bd35,0x3d80,0x3d35bd35,0xbd800000,0x3d353d35,0xbd80,0xbd353d35,0x3d800000,0xbd35bd35,
0x3d80,0x3d35bd35,0xbd800000,0x3d353d35,0xbd80,0xbd353d35,0x3d800000,0xbd35bd35,0x3d80,0x3d35bd35,0xbd800000,0x3d353d35,0xbd80,0xbd353d35,0x3d800000,0xbd35bd35,
0xbd353d35,0x3d7b3c48,0xbcc4bd6d,0xbd0e3d55,0xbd80,0xbd553d0e,0x3d6d3cc4,0xbc48bd7b,0xbd35bd35,0xbc483d7b,0x3d6dbcc4,0xbd55bd0e,0x3d800000,0xbd0ebd55,0xbcc43d6d,0x3d7bbc48,
0x3d35bd35,0xbd7bbc48,0x3cc43d6d,0x3d0ebd55,0x3d80,0x3d55bd0e,0xbd6dbcc4,0x3c483d7b,0x3d353d35,0x3c48bd7b,0xbd6d3cc4,0x3d553d0e,0xbd800000,0x3d0e3d55,0x3cc4bd6d,0xbd7b3c48,
0xbd80,0xbd6d3cc4,0x3d353d35,0x3cc4bd6d,0xbd800000,0x3cc43d6d,0x3d35bd35,0xbd6dbcc4,0x3d80,0x3d6dbcc4,0xbd35bd35,0xbcc43d6d,0x3d800000,0xbcc4bd6d,0xbd353d35,0x3d6d3cc4,
0xbd80,0xbd6d3cc4,0x3d353d35,0x3cc4bd6d,0xbd800000,0x3cc43d6d,0x3d35bd35,0xbd6dbcc4,0x3d80,0x3d6dbcc4,0xbd35bd35,0xbcc43d6d,0x3d800000,0xbcc4bd6d,0xbd353d35,0x3d6d3cc4,
0xbd353d35,0x3d553d0e,0x3cc4bd6d,0xbd7bbc48,0xbd800000,0x3c483d7b,0x3d6dbcc4,0xbd0ebd55,0xbd35bd35,0xbd0e3d55,0x3d6d3cc4,0x3c48bd7b,0xbd80,0xbd7b3c48,0x3cc43d6d,0x3d55bd0e,
0x3d35bd35,0xbd55bd0e,0xbcc43d6d,0x3d7b3c48,0x3d800000,0xbc48bd7b,0xbd6d3cc4,0x3d0e3d55,0x3d353d35,0x3d0ebd55,0xbd6dbcc4,0xbc483d7b,0x3d80,0x3d7bbc48,0xbcc4bd6d,0xbd553d0e,
0xbd800000,0x3d800000,0xbd800000,0x3d800000,0xbd800000,0x3d800000,0xbd800000,0x3d800000,0xbd800000,0x3d800000,0xbd800000,0x3d800000,0xbd800000,0x3d800000,0xbd800000,0x3d800000,
0xbd800000,0x3d800000,0xbd800000,0x3d800000,0xbd800000,0x3d800000,0xbd800000,0x3d800000,0xbd800000,0x3d800000,0xbd800000,0x3d800000,0xbd800000,0x3d800000,0xbd800000,0x3d800000,
0xbd35bd35,0x3d0e3d55,0xbcc4bd6d,0x3c483d7b,0xbd800000,0x3d7b3c48,0xbd6dbcc4,0x3d553d0e,0x3d35bd35,0xbd553d0e,0x3d6dbcc4,0xbd7b3c48,0x8000bd80,0xbc483d7b,0x3cc4bd6d,0xbd0e3d55,
0x3d353d35,0xbd0ebd55,0x3cc43d6d,0xbc48bd7b,0x3d800000,0xbd7bbc48,0x3d6d3cc4,0xbd55bd0e,0xbd353d35,0x3d55bd0e,0xbd6d3cc4,0x3d7bbc48,0x80003d80,0x3c48bd7b,0xbcc43d6d,0x3d0ebd55,
0x3d800000,0xbd6dbcc4,0x3d353d35,0xbcc4bd6d,0x80003d80,0x3cc4bd6d,0xbd353d35,0x3d6dbcc4,0xbd800000,0x3d6d3cc4,0xbd35bd35,0x3cc43d6d,0x8000bd80,0xbcc43d6d,0x3d35bd35,0xbd6d3cc4,
0x3d800000,0xbd6dbcc4,0x3d353d35,0xbcc4bd6d,0x80003d80,0x3cc4bd6d,0xbd353d35,0x3d6dbcc4,0xbd800000,0x3d6d3cc4,0xbd35bd35,0x3cc43d6d,0x8000bd80,0xbcc43d6d,0x3d35bd35,0xbd6d3cc4,
0xbd35bd35,0x3c483d7b,0x3cc4bd6d,0xbd553d0e,0x80003d80,0x3d0ebd55,0xbd6d3cc4,0x3d7b3c48,0x3d35bd35,0xbd7b3c48,0x3d6d3cc4,0xbd0ebd55,0xbd800000,0x3d553d0e,0xbcc4bd6d,0xbc483d7b,
0x3d353d35,0xbc48bd7b,0xbcc43d6d,0x3d55bd0e,0x8000bd80,0xbd0e3d55,0x3d6dbcc4,0xbd7bbc48,0xbd353d35,0x3d7bbc48,0xbd6dbcc4,0x3d0e3d55,0x3d800000,0xbd55bd0e,0x3cc43d6d,0x3c48bd7b,
0xbd800000,0x3d353d35,0x8000bd80,0xbd353d35,0x3d800000,0xbd35bd35,0x80003d80,0x3d35bd35,0xbd800000,0x3d353d35,0x8000bd80,0xbd353d35,0x3d800000,0xbd35bd35,0x80003d80,0x3d35bd35,
0xbd800000,0x3d353d35,0x8000bd80,0xbd353d35,0x3d800000,0xbd35bd35,0x80003d80,0x3d35bd35,0xbd800000,0x3d353d35,0x8000bd80,0xbd353d35,0x3d800000,0xbd35bd35,0x80003d80,0x3d35bd35,
0xbd35bd35,0xbc483d7b,0x3d6dbcc4,0xbd55bd0e,0x3d800000,0xbd0ebd55,0xbcc43d6d,0x3d7bbc48,0x3d35bd35,0xbd7bbc48,0x3cc43d6d,0x3d0ebd55,0x80003d80,0x3d55bd0e,0xbd6dbcc4,0x3c483d7b,
0x3d353d35,0x3c48bd7b,0xbd6d3cc4,0x3d553d0e,0xbd800000,0x3d0e3d55,0x3cc4bd6d,0xbd7b3c48,0xbd353d35,0x3d7b3c48,0xbcc4bd6d,0xbd0e3d55,0x8000bd80,0xbd553d0e,0x3d6d3cc4,0xbc48bd7b,
0x3d800000,0xbcc4bd6d,0xbd353d35,0x3d6d3cc4,0x8000bd80,0xbd6d3cc4,0x3d353d35,0x3cc4bd6d,0xbd800000,0x3cc43d6d,0x3d35bd35,0xbd6dbcc4,0x80003d80,0x3d6dbcc4,0xbd35bd35,0xbcc43d6d,
0x3d800000,0xbcc4bd6d,0xbd353d35,0x3d6d3cc4,0x8000bd80,0xbd6d3cc4,0x3d353d35,0x3cc4bd6d,0xbd800000,0x3cc43d6d,0x3d35bd35,0xbd6dbcc4,0x80003d80,0x3d6dbcc4,0xbd35bd35,0xbcc43d6d,
0xbd35bd35,0xbd0e3d55,0x3d6d3cc4,0x3c48bd7b,0x8000bd80,0xbd7b3c48,0x3cc43d6d,0x3d55bd0e,0x3d35bd35,0xbd55bd0e,0xbcc43d6d,0x3d7b3c48,0x3d800000,0xbc48bd7b,0xbd6d3cc4,0x3d0e3d55,
0x3d353d35,0x3d0ebd55,0xbd6dbcc4,0xbc483d7b,0x80003d80,0x3d7bbc48,0xbcc4bd6d,0xbd553d0e,0xbd353d35,0x3d553d0e,0x3cc4bd6d,0xbd7bbc48,0xbd800000,0x3c483d7b,0x3d6dbcc4,0xbd0ebd55,
0x3d80,0x3d800000,0xbd80,0xbd800000,0x3d80,0x3d800000,0xbd80,0xbd800000,0x3d80,0x3d800000,0xbd80,0xbd800000,0x3d80,0x3d800000,0xbd80,0xbd800000,
0x3d80,0x3d800000,0xbd80,0xbd800000,0x3d80,0x3d800000,0xbd80,0xbd800000,0x3d80,0x3d800000,0xbd80,0xbd800000,0x3d80,0x3d800000,0xbd80,0xbd800000,
0xbd353d35,0x3d0e3d55,0x3d6dbcc4,0xbc48bd7b,0x3d80,0x3d7b3c48,0x3cc4bd6d,0xbd55bd0e,0xbd35bd35,0xbd553d0e,0x3cc43d6d,0x3d7bbc48,0xbd800000,0xbc483d7b,0x3d6d3cc4,0x3d0ebd55,
0x3d35bd35,0xbd0ebd55,0xbd6d3cc4,0x3c483d7b,0xbd80,0xbd7bbc48,0xbcc43d6d,0x3d553d0e,0x3d353d35,0x3d55bd0e,0xbcc4bd6d,0xbd7b3c48,0x3d800000,0x3c48bd7b,0xbd6dbcc4,0xbd0e3d55,
0xbd80,0xbd6dbcc4,0xbd353d35,0x3cc43d6d,0x3d800000,0x3cc4bd6d,0xbd35bd35,0xbd6d3cc4,0x3d80,0x3d6d3cc4,0x3d35bd35,0xbcc4bd6d,0xbd800000,0xbcc43d6d,0x3d353d35,0x3d6dbcc4,
0xbd80,0xbd6dbcc4,0xbd353d35,0x3cc43d6d,0x3d800000,0x3cc4bd6d,0xbd35bd35,0xbd6d3cc4,0x3d80,0x3d6d3cc4,0x3d35bd35,0xbcc4bd6d,0xbd800000,0xbcc43d6d,0x3d353d35,0x3d6dbcc4,
0xbd353d35,0x3c483d7b,0x3d6d3cc4,0x3d55bd0e,0x3d800000,0x3d0ebd55,0xbcc4bd6d,0xbd7bbc48,0xbd35bd35,0xbd7b3c48,0xbcc43d6d,0x3d0e3d55,0x3d80,0x3d553d0e,0x3d6dbcc4,0x3c48bd7b,
0x3d35bd35,0xbc48bd7b,0xbd6dbcc4,0xbd553d0e,0xbd800000,0xbd0e3d55,0x3cc43d6d,0x3d7b3c48,0x3d353d35,0x3d7bbc48,0x3cc4bd6d,0xbd0ebd55,0xbd80,0xbd55bd0e,0xbd6d3cc4,0xbc483d7b,
0x3d80,0x3d353d35,0x3d800000,0x3d35bd35,0xbd80,0xbd35bd35,0xbd800000,0xbd353d35,0x3d80,0x3d353d35,0x3d800000,0x3d35bd35,0xbd80,0xbd35bd35,0xbd800000,0xbd353d35,
0x3d80,0x3d353d35,0x3d800000,0x3d35bd35,0xbd80,0xbd35bd35,0xbd800000,0xbd353d35,0x3d80,0x3d353d35,0x3d800000,0x3d35bd35,0xbd80,0xbd35bd35,0xbd800000,0xbd353d35,
0xbd353d35,0xbc483d7b,0x3cc43d6d,0x3d553d0e,0xbd80,0xbd0ebd55,0xbd6dbcc4,0xbd7b3c48,0xbd35bd35,0xbd7bbc48,0xbd6d3cc4,0xbd0e3d55,0x3d800000,0x3d55bd0e,0x3cc4bd6d,0xbc48bd7b,
0x3d35bd35,0x3c48bd7b,0xbcc4bd6d,0xbd55bd0e,0x3d80,0x3d0e3d55,0x3d6d3cc4,0x3d7bbc48,0x3d353d35,0x3d7b3c48,0x3d6dbcc4,0x3d0ebd55,0xbd800000,0xbd553d0e,0xbcc43d6d,0x3c483d7b,
0xbd80,0xbcc4bd6d,0xbd35bd35,0xbd6dbcc4,0xbd800000,0xbd6d3cc4,0xbd353d35,0xbcc43d6d,0x3d80,0x3cc43d6d,0x3d353d35,0x3d6d3cc4,0x3d800000,0x3d6dbcc4,0x3d35bd35,0x3cc4bd6d,
0xbd80,0xbcc4bd6d,0xbd35bd35,0xbd6dbcc4,0xbd800000,0xbd6d3cc4,0xbd353d35,0xbcc43d6d,0x3d80,0x3cc43d6d,0x3d353d35,0x3d6d3cc4,0x3d800000,0x3d6dbcc4,0x3d35bd35,0x3cc4bd6d,
0xbd353d35,0xbd0e3d55,0xbcc43d6d,0xbc483d7b,0xbd800000,0xbd7b3c48,0xbd6d3cc4,0xbd553d0e,0xbd35bd35,0xbd55bd0e,0xbd6dbcc4,0xbd7bbc48,0xbd80,0xbc48bd7b,0xbcc4bd6d,0xbd0ebd55,
0x3d35bd35,0x3d0ebd55,0x3cc4bd6d,0x3c48bd7b,0x3d800000,0x3d7bbc48,0x3d6dbcc4,0x3d55bd0e,0x3d353d35,0x3d553d0e,0x3d6d3cc4,0x3d7b3c48,0x3d80,0x3c483d7b,0x3cc43d6d,0x3d0e3d55,
0xbd800000,0x80003d80,0x3d800000,0x8000bd80,0xbd800000,0x80003d80,0x3d800000,0x8000bd80,0xbd800000,0x80003d80,0x3d800000,0x8000bd80,0xbd800000,0x80003d80,0x3d800000,0x8000bd80,
0xbd800000,0x80003d80,0x3d800000,0x8000bd80,0xbd800000,0x80003d80,0x3d800000,0x8000bd80,0xbd800000,0x80003d80,0x3d800000,0x8000bd80,0xbd800000,0x80003d80,0x3d800000,0x8000bd80,
0xbd35bd35,0xbd553d0e,0x3cc43d6d,0x3d7bbc48,0xbd800000,0xbc483d7b,0x3d6d3cc4,0x3d0ebd55,0x3d35bd35,0xbd0ebd55,0xbd6d3cc4,0x3c483d7b,0x8000bd80,0xbd7bbc48,0xbcc43d6d,0x3d553d0e,
0x3d353d35,0x3d55bd0e,0xbcc4bd6d,0xbd7b3c48,0x3d800000,0x3c48bd7b,0xbd6dbcc4,0xbd0e3d55,0xbd353d35,0x3d0e3d55,0x3d6dbcc4,0xbc48bd7b,0x80003d80,0x3d7b3c48,0x3cc4bd6d,0xbd55bd0e,
0x3d800000,0x3cc4bd6d,0xbd35bd35,0xbd6d3cc4,0x80003d80,0x3d6d3cc4,0x3d35bd35,0xbcc4bd6d,0xbd800000,0xbcc43d6d,0x3d353d35,0x3d6dbcc4,0x8000bd80,0xbd6dbcc4,0xbd353d35,0x3cc43d6d,
0x3d800000,0x3cc4bd6d,0xbd35bd35,0xbd6d3cc4,0x80003d80,0x3d6d3cc4,0x3d35bd35,0xbcc4bd6d,0xbd800000,0xbcc43d6d,0x3d353d35,0x3d6dbcc4,0x8000bd80,0xbd6dbcc4,0xbd353d35,0x3cc43d6d,
0xbd35bd35,0xbd7b3c48,0xbcc43d6d,0x3d0e3d55,0x80003d80,0x3d553d0e,0x3d6dbcc4,0x3c48bd7b,0x3d35bd35,0xbc48bd7b,0xbd6dbcc4,0xbd553d0e,0xbd800000,0xbd0e3d55,0x3cc43d6d,0x3d7b3c48,
0x3d353d35,0x3d7bbc48,0x3cc4bd6d,0xbd0ebd55,0x8000bd80,0xbd55bd0e,0xbd6d3cc4,0xbc483d7b,0xbd353d35,0x3c483d7b,0x3d6d3cc4,0x3d55bd0e,0x3d800000,0x3d0ebd55,0xbcc4bd6d,0xbd7bbc48,
0xbd800000,0xbd353d35,0x80003d80,0x3d353d35,0x3d800000,0x3d35bd35,0x8000bd80,0xbd35bd35,0xbd800000,0xbd353d35,0x80003d80,0x3d353d35,0x3d800000,0x3d35bd35,0x8000bd80,0xbd35bd35,
0xbd800000,0xbd353d35,0x80003d80,0x3d353d35,0x3d800000,0x3d35bd35,0x8000bd80,0xbd35bd35,0xbd800000,0xbd353d35,0x80003d80,0x3d353d35,0x3d800000,0x3d35bd35,0x8000bd80,0xbd35bd35,
0xbd35bd35,0xbd7bbc48,0xbd6d3cc4,0xbd0e3d55,0x3d800000,0x3d55bd0e,0x3cc4bd6d,0xbc48bd7b,0x3d35bd35,0x3c48bd7b,0xbcc4bd6d,0xbd55bd0e,0x80003d80,0x3d0e3d55,0x3d6d3cc4,0x3d7bbc48,
0x3d353d35,0x3d7b3c48,0x3d6dbcc4,0x3d0ebd55,0xbd800000,0xbd553d0e,0xbcc43d6d,0x3c483d7b,0xbd353d35,0xbc483d7b,0x3cc43d6d,0x3d553d0e,0x8000bd80,0xbd0ebd55,0xbd6dbcc4,0xbd7b3c48,
0x3d800000,0x3d6dbcc4,0x3d35bd35,0x3cc4bd6d,0x8000bd80,0xbcc4bd6d,0xbd35bd35,0xbd6dbcc4,0xbd800000,0xbd6d3cc4,0xbd353d35,0xbcc43d6d,0x80003d80,0x3cc43d6d,0x3d353d35,0x3d6d3cc4,
0x3d800000,0x3d6dbcc4,0x3d35bd35,0x3cc4bd6d,0x8000bd80,0xbcc4bd6d,0xbd35bd35,0xbd6dbcc4,0xbd800000,0xbd6d3cc4,0xbd353d35,0xbcc43d6d,0x80003d80,0x3cc43d6d,0x3d353d35,0x3d6d3cc4,
0xbd35bd35,0xbd55bd0e,0xbd6dbcc4,0xbd7bbc48,0x8000bd80,0xbc48bd7b,0xbcc4bd6d,0xbd0ebd55,0x3d35bd35,0x3d0ebd55,0x3cc4bd6d,0x3c48bd7b,0x3d800000,0x3d7bbc48,0x3d6dbcc4,0x3d55bd0e,
0x3d353d35,0x3d553d0e,0x3d6d3cc4,0x3d7b3c48,0x80003d80,0x3c483d7b,0x3cc43d6d,0x3d0e3d55,0xbd353d35,0xbd0e3d55,0xbcc43d6d,0xbc483d7b,0xbd800000,0xbd7b3c48,0xbd6d3cc4,0xbd553d0e,
0x3d80,0xbb493d80,0xbbc93d7f,0xbc163d7d,0xbc483d7b,0xbc793d78,0xbc953d75,0xbcac3d71,0xbcc43d6d,0xbcdb3d67,0xbcf13d62,0xbd043d5c,0xbd0e3d55,0xbd183d4e,0xbd223d46,0xbd2c3d3e,
0xbd353d35,0xbd3e3d2c,0xbd463d22,0xbd4e3d18,0xbd553d0e,0xbd5c3d04,0xbd623cf1,0xbd673cdb,0xbd6d3cc4,0xbd713cac,0xbd753c95,0xbd783c79,0xbd7b3c48,0xbd7d3c16,0xbd7f3bc9,0xbd803b49,
0xbd553d0e,0xbd713cac,0xbd7f3bc9,0xbd7dbc16,0x3d80,0xbc793d78,0xbcf13d62,0xbd2c3d3e,0xbc48bd7b,0x3b49bd80,0x3c95bd75,0x3d04bd5c,0xbd6dbcc4,0xbd4ebd18,0xbd22bd46,0xbcdbbd67,
0x3d7b3c48,0x3d673cdb,0x3d463d22,0x3d183d4e,0x3d35bd35,0x3d5cbd04,0x3d75bc95,0x3d80bb49,0xbd0e3d55,0xbd3e3d2c,0xbd623cf1,0xbd783c79,0x3cc43d6d,0x3c163d7d,0xbbc93d7f,0xbcac3d71,
0x3cc4bd6d,0x3d3ebd2c,0x3d75bc95,0x3d7d3c16,0x3d553d0e,0x3d043d5c,0x3bc93d7f,0xbcac3d71,0x3d80,0xbcdb3d67,0xbd463d22,0xbd783c79,0xbd7bbc48,0xbd4ebd18,0xbcf1bd62,0xbb49bd80,
0x3d6dbcc4,0x3d803b49,0x3d623cf1,0x3d183d4e,0x3c483d7b,0xbc793d78,0xbd223d46,0xbd673cdb,0xbd353d35,0xbd713cac,0xbd7fbbc9,0xbd5cbd04,0xbd0ebd55,0xbc16bd7d,0x3c95bd75,0x3d2cbd3e,
0xbd7b3c48,0xbd67bcdb,0xbcf1bd62,0x3c16bd7d,0x3d6d3cc4,0x3d043d5c,0xbbc93d7f,0xbd2c3d3e,0xbd0ebd55,0x3b49bd80,0x3d22bd46,0x3d78bc79,0x3d80,0xbd183d4e,0xbd753c95,0xbd71bcac,
0x3d553d0e,0x3cac3d71,0xbc953d75,0xbd4e3d18,0xbcc4bd6d,0x3c79bd78,0x3d46bd22,0x3d80bb49,0xbc483d7b,0xbd3e3d2c,0xbd7f3bc9,0xbd5cbd04,0x3d35bd35,0x3d7dbc16,0x3d623cf1,0x3cdb3d67,
0xbd353d35,0xbd80bb49,0xbd22bd46,0x3c16bd7d,0x3d55bd0e,0x3d783c79,0x3cf13d62,0xbcac3d71,0xbd6d3cc4,0xbd67bcdb,0xbc95bd75,0x3d04bd5c,0x3d7bbc48,0x3d4e3d18,0x3bc93d7f,0xbd2c3d3e,
0x3d80,0xbd3e3d2c,0xbd7fbbc9,0xbd18bd4e,0x3c48bd7b,0x3d5cbd04,0x3d753c95,0x3cdb3d67,0xbcc43d6d,0xbd713cac,0xbd62bcf1,0xbc79bd78,0x3d0ebd55,0x3d7dbc16,0x3d463d22,0x3b493d80,
0xbd7bbc48,0xbcacbd71,0x3d22bd46,0x3d7d3c16,0x3d35bd35,0x3d783c79,0x3c953d75,0xbd2c3d3e,0x3d0ebd55,0x3d803b49,0x3cf13d62,0xbd043d5c,0x3cc43d6d,0xbd183d4e,0xbd7fbbc9,0xbcdbbd67,
0x3d55bd0e,0x3d673cdb,0x3bc93d7f,0xbd4e3d18,0x3d80,0xbd5c3d04,0xbd62bcf1,0xbb49bd80,0x3c483d7b,0xbd3e3d2c,0xbd75bc95,0xbc79bd78,0xbd6dbcc4,0xbc16bd7d,0x3d46bd22,0x3d713cac,
0x3d6dbcc4,0x3d2c3d3e,0xbcf13d62,0xbd7dbc16,0xbc48bd7b,0x3d5cbd04,0x3d463d22,0xbcac3d71,0xbd353d35,0xbd67bcdb,0x3bc9bd7f,0x3d78bc79,0x3d0e3d55,0xbd183d4e,0xbd75bc95,0xbb49bd80,
0x3cc4bd6d,0x3d803b49,0x3c953d75,0xbd4e3d18,0xbd55bd0e,0x3c79bd78,0x3d7fbbc9,0x3cdb3d67,0x3d80,0xbd713cac,0xbd22bd46,0x3d04bd5c,0x3d7b3c48,0x3c163d7d,0xbd623cf1,0xbd3ebd2c,
0xbd55bd0e,0x3cdbbd67,0x3d753c95,0xbc163d7d,0xbcc4bd6d,0x3d5cbd04,0x3d223d46,0xbd2c3d3e,0x3c48bd7b,0x3d803b49,0x3bc93d7f,0xbd783c79,0x3d35bd35,0x3d4e3d18,0xbcf13d62,0xbd71bcac,
0x3d7bbc48,0x3cac3d71,0xbd623cf1,0xbd18bd4e,0x3d6d3cc4,0xbc793d78,0xbd7fbbc9,0xbb49bd80,0x3d0e3d55,0xbd3e3d2c,0xbd46bd22,0x3d04bd5c,0x3d80,0xbd7d3c16,0xbc95bd75,0x3d67bcdb,
0xbd800000,0xbd80bb49,0xbd7fbbc9,0xbd7dbc16,0xbd7bbc48,0xbd78bc79,0xbd75bc95,0xbd71bcac,0xbd6dbcc4,0xbd67bcdb,0xbd62bcf1,0xbd5cbd04,0xbd55bd0e,0xbd4ebd18,0xbd46bd22,0xbd3ebd2c,
0xbd35bd35,0xbd2cbd3e,0xbd22bd46,0xbd18bd4e,0xbd0ebd55,0xbd04bd5c,0xbcf1bd62,0xbcdbbd67,0xbcc4bd6d,0xbcacbd71,0xbc95bd75,0xbc79bd78,0xbc48bd7b,0xbc16bd7d,0xbbc9bd7f,0xbb49bd80,
0xbd0ebd55,0xbcacbd71,0xbbc9bd7f,0x3c16bd7d,0xbd800000,0xbd78bc79,0xbd62bcf1,0xbd3ebd2c,0x3d7bbc48,0x3d803b49,0x3d753c95,0x3d5c3d04,0x3cc4bd6d,0x3d18bd4e,0x3d46bd22,0x3d67bcdb,
0xbc483d7b,0xbcdb3d67,0xbd223d46,0xbd4e3d18,0x3d353d35,0x3d043d5c,0x3c953d75,0x3b493d80,0xbd55bd0e,0xbd2cbd3e,0xbcf1bd62,0xbc79bd78,0xbd6d3cc4,0xbd7d3c16,0xbd7fbbc9,0xbd71bcac,
0x3d6d3cc4,0x3d2c3d3e,0x3c953d75,0xbc163d7d,0xbd0e3d55,0xbd5c3d04,0xbd7f3bc9,0xbd71bcac,0xbd800000,0xbd67bcdb,0xbd22bd46,0xbc79bd78,0x3c48bd7b,0x3d18bd4e,0x3d62bcf1,0x3d80bb49,
0x3cc43d6d,0xbb493d80,0xbcf13d62,0xbd4e3d18,0xbd7b3c48,0xbd78bc79,0xbd46bd22,0xbcdbbd67,0xbd35bd35,0xbcacbd71,0x3bc9bd7f,0x3d04bd5c,0x3d55bd0e,0x3d7dbc16,0x3d753c95,0x3d3e3d2c,
0xbc48bd7b,0x3cdbbd67,0x3d62bcf1,0x3d7d3c16,0xbcc43d6d,0xbd5c3d04,0xbd7fbbc9,0xbd3ebd2c,0x3d55bd0e,0x3d803b49,0x3d463d22,0x3c793d78,0xbd800000,0xbd4ebd18,0xbc95bd75,0x3cacbd71,
0xbd0e3d55,0xbd713cac,0xbd75bc95,0xbd18bd4e,0x3d6dbcc4,0x3d783c79,0x3d223d46,0x3b493d80,0xbd7bbc48,0xbd2cbd3e,0xbbc9bd7f,0x3d04bd5c,0x3d353d35,0x3c163d7d,0xbcf13d62,0xbd673cdb,
0xbd35bd35,0x3b49bd80,0x3d46bd22,0x3d7d3c16,0x3d0e3d55,0xbc793d78,0xbd623cf1,0xbd71bcac,0xbcc4bd6d,0x3cdbbd67,0x3d75bc95,0x3d5c3d04,0x3c483d7b,0xbd183d4e,0xbd7f3bc9,0xbd3ebd2c,
0xbd800000,0xbd2cbd3e,0x3bc9bd7f,0x3d4ebd18,0x3d7b3c48,0x3d043d5c,0xbc953d75,0xbd673cdb,0xbd6dbcc4,0xbcacbd71,0x3cf1bd62,0x3d78bc79,0x3d553d0e,0x3c163d7d,0xbd223d46,0xbd803b49,
0x3c48bd7b,0x3d71bcac,0x3d463d22,0xbc163d7d,0x3d353d35,0xbc793d78,0xbd753c95,0xbd3ebd2c,0x3d553d0e,0xbb493d80,0xbd623cf1,0xbd5cbd04,0xbd6d3cc4,0xbd4ebd18,0x3bc9bd7f,0x3d67bcdb,
0x3d0e3d55,0xbcdb3d67,0xbd7f3bc9,0xbd18bd4e,0xbd800000,0xbd04bd5c,0x3cf1bd62,0x3d80bb49,0xbd7b3c48,0xbd2cbd3e,0x3c95bd75,0x3d78bc79,0x3cc4bd6d,0x3d7dbc16,0x3d223d46,0xbcac3d71,
0x3cc43d6d,0xbd3e3d2c,0xbd62bcf1,0x3c16bd7d,0x3d7bbc48,0x3d043d5c,0xbd223d46,0xbd71bcac,0xbd35bd35,0x3cdbbd67,0x3d7f3bc9,0x3c793d78,0xbd553d0e,0xbd4ebd18,0x3c95bd75,0x3d80bb49,
0x3d6d3cc4,0xbb493d80,0xbd753c95,0xbd18bd4e,0x3d0ebd55,0x3d783c79,0x3bc93d7f,0xbd673cdb,0xbd800000,0xbcacbd71,0x3d46bd22,0x3d5c3d04,0xbc483d7b,0xbd7d3c16,0xbcf1bd62,0x3d2cbd3e,
0x3d0ebd55,0x3d673cdb,0xbc953d75,0xbd7dbc16,0x3d6dbcc4,0x3d043d5c,0xbd463d22,0xbd3ebd2c,0x3d7b3c48,0xbb493d80,0xbd7f3bc9,0xbc79bd78,0x3d353d35,0xbd183d4e,0xbd62bcf1,0x3cacbd71,
0x3c483d7b,0xbd713cac,0xbcf1bd62,0x3d4ebd18,0xbcc43d6d,0xbd78bc79,0x3bc9bd7f,0x3d80bb49,0xbd553d0e,0xbd2cbd3e,0x3d22bd46,0x3d5c3d04,0xbd800000,0xbc16bd7d,0x3d75bc95,0x3cdb3d67,
0x3d80,0xbd80bb49,0x3bc9bd7f,0x3d7d3c16,0xbc483d7b,0xbd78bc79,0x3c95bd75,0x3d713cac,0xbcc43d6d,0xbd67bcdb,0x3cf1bd62,0x3d5c3d04,0xbd0e3d55,0xbd4ebd18,0x3d22bd46,0x3d3e3d2c,
0xbd353d35,0xbd2cbd3e,0x3d46bd22,0x3d183d4e,0xbd553d0e,0xbd04bd5c,0x3d62bcf1,0x3cdb3d67,0xbd6d3cc4,0xbcacbd71,0x3d75bc95,0x3c793d78,0xbd7b3c48,0xbc16bd7d,0x3d7fbbc9,0x3b493d80,
0xbd553d0e,0xbcacbd71,0x3d7fbbc9,0xbc163d7d,0x3d80,0xbd78bc79,0x3cf1bd62,0x3d3e3d2c,0xbc48bd7b,0x3d803b49,0xbc953d75,0xbd5cbd04,0xbd6dbcc4,0x3d18bd4e,0x3d223d46,0xbd673cdb,
0x3d7b3c48,0xbcdb3d67,0xbd46bd22,0x3d4ebd18,0x3d35bd35,0x3d043d5c,0xbd753c95,0xbb49bd80,0xbd0e3d55,0xbd2cbd3e,0x3d62bcf1,0x3c793d78,0x3cc43d6d,0xbd7d3c16,0x3bc9bd7f,0x3d713cac,
0x3cc4bd6d,0x3d2c3d3e,0xbd753c95,0x3c16bd7d,0x3d553d0e,0xbd5c3d04,0xbbc9bd7f,0x3d713cac,0x3d80,0xbd67bcdb,0x3d46bd22,0x3c793d78,0xbd7bbc48,0x3d18bd4e,0x3cf13d62,0xbd803b49,
0x3d6dbcc4,0xbb493d80,0xbd62bcf1,0x3d4ebd18,0x3c483d7b,0xbd78bc79,0x3d22bd46,0x3cdb3d67,0xbd353d35,0xbcacbd71,0x3d7f3bc9,0xbd043d5c,0xbd0ebd55,0x3d7dbc16,0xbc953d75,0xbd3ebd2c,
0xbd7b3c48,0x3cdbbd67,0x3cf13d62,0xbd7dbc16,0x3d6d3cc4,0xbd5c3d04,0x3bc9bd7f,0x3d3e3d2c,0xbd0ebd55,0x3d803b49,0xbd223d46,0xbc79bd78,0x3d80,0xbd4ebd18,0x3d75bc95,0xbcac3d71,
0x3d553d0e,0xbd713cac,0x3c95bd75,0x3d183d4e,0xbcc4bd6d,0x3d783c79,0xbd463d22,0xbb49bd80,0xbc483d7b,0xbd2cbd3e,0x3d7fbbc9,0xbd043d5c,0x3d35bd35,0x3c163d7d,0xbd62bcf1,0x3d67bcdb,
0xbd353d35,0x3b49bd80,0x3d223d46,0xbd7dbc16,0x3d55bd0e,0xbc793d78,0xbcf1bd62,0x3d713cac,0xbd6d3cc4,0x3cdbbd67,0x3c953d75,0xbd5cbd04,0x3d7bbc48,0xbd183d4e,0xbbc9bd7f,0x3d3e3d2c,
0x3d80,0xbd2cbd3e,0x3d7f3bc9,0xbd4e3d18,0x3c48bd7b,0x3d043d5c,0xbd75bc95,0x3d67bcdb,0xbcc43d6d,0xbcacbd71,0x3d623cf1,0xbd783c79,0x3d0ebd55,0x3c163d7d,0xbd46bd22,0x3d80bb49,
0xbd7bbc48,0x3d71bcac,0xbd223d46,0x3c16bd7d,0x3d35bd35,0xbc793d78,0xbc95bd75,0x3d3e3d2c,0x3d0ebd55,0xbb493d80,0xbcf1bd62,0x3d5c3d04,0x3cc43d6d,0xbd4ebd18,0x3d7f3bc9,0xbd673cdb,
0x3d55bd0e,0xbcdb3d67,0xbbc9bd7f,0x3d183d4e,0x3d80,0xbd04bd5c,0x3d623cf1,0xbd803b49,0x3c483d7b,0xbd2cbd3e,0x3d753c95,0xbd783c79,0xbd6dbcc4,0x3d7dbc16,0xbd463d22,0x3cacbd71,
0x3d6dbcc4,0xbd3e3d2c,0x3cf1bd62,0xbc163d7d,0xbc48bd7b,0x3d043d5c,0xbd46bd22,0x3d713cac,0xbd353d35,0x3cdbbd67,0xbbc93d7f,0xbc79bd78,0x3d0e3d55,0xbd4ebd18,0x3d753c95,0xbd803b49,
0x3cc4bd6d,0xbb493d80,0xbc95bd75,0x3d183d4e,0xbd55bd0e,0x3d783c79,0xbd7f3bc9,0x3d67bcdb,0x3d80,0xbcacbd71,0x3d223d46,0xbd5cbd04,0x3d7b3c48,0xbd7d3c16,0x3d62bcf1,0xbd2c3d3e,
0xbd55bd0e,0x3d673cdb,0xbd75bc95,0x3d7d3c16,0xbcc4bd6d,0x3d043d5c,0xbd22bd46,0x3d3e3d2c,0x3c48bd7b,0xbb493d80,0xbbc9bd7f,0x3c793d78,0x3d35bd35,0xbd183d4e,0x3cf1bd62,0xbcac3d71,
0x3d7bbc48,0xbd713cac,0x3d62bcf1,0xbd4e3d18,0x3d6d3cc4,0xbd78bc79,0x3d7f3bc9,0xbd803b49,0x3d0e3d55,0xbd2cbd3e,0x3d463d22,0xbd5cbd04,0x3d80,0xbc16bd7d,0x3c953d75,0xbcdbbd67,
0xbd800000,0x3b49bd80,0x3d7f3bc9,0xbc163d7d,0xbd7bbc48,0x3c79bd78,0x3d753c95,0xbcac3d71,0xbd6dbcc4,0x3cdbbd67,0x3d623cf1,0xbd043d5c,0xbd55bd0e,0x3d18bd4e,0x3d463d22,0xbd2c3d3e,
0xbd35bd35,0x3d3ebd2c,0x3d223d46,0xbd4e3d18,0xbd0ebd55,0x3d5cbd04,0x3cf13d62,0xbd673cdb,0xbcc4bd6d,0x3d71bcac,0x3c953d75,0xbd783c79,0xbc48bd7b,0x3d7dbc16,0x3bc93d7f,0xbd803b49,
0xbd0ebd55,0x3d71bcac,0x3bc93d7f,0xbd7dbc16,0xbd800000,0x3c79bd78,0x3d623cf1,0xbd2c3d3e,0x3d7bbc48,0xbb493d80,0xbd75bc95,0x3d04bd5c,0x3cc4bd6d,0x3d4e3d18,0xbd463d22,0xbcdbbd67,
0xbc483d7b,0xbd67bcdb,0x3d22bd46,0x3d183d4e,0x3d353d35,0xbd5c3d04,0xbc95bd75,0x3d80bb49,0xbd55bd0e,0x3d3ebd2c,0x3cf13d62,0xbd783c79,0xbd6d3cc4,0xbc16bd7d,0x3d7f3bc9,0xbcac3d71,
0x3d6d3cc4,0xbd3e3d2c,0xbc95bd75,0x3d7d3c16,0xbd0e3d55,0xbd04bd5c,0x3d7fbbc9,0xbcac3d71,0xbd800000,0x3cdbbd67,0x3d223d46,0xbd783c79,0x3c48bd7b,0x3d4e3d18,0xbd623cf1,0xbb49bd80,
0x3cc43d6d,0xbd80bb49,0x3cf1bd62,0x3d183d4e,0xbd7b3c48,0x3c79bd78,0x3d463d22,0xbd673cdb,0xbd35bd35,0x3d71bcac,0xbbc93d7f,0xbd5cbd04,0x3d55bd0e,0x3c163d7d,0xbd75bc95,0x3d2cbd3e,
0xbc48bd7b,0x3d673cdb,0xbd623cf1,0x3c16bd7d,0xbcc43d6d,0xbd04bd5c,0x3d7f3bc9,0xbd2c3d3e,0x3d55bd0e,0xbb493d80,0xbd46bd22,0x3d78bc79,0xbd800000,0x3d18bd4e,0x3c953d75,0xbd71bcac,
0xbd0e3d55,0xbcacbd71,0x3d753c95,0xbd4e3d18,0x3d6dbcc4,0xbc793d78,0xbd22bd46,0x3d80bb49,0xbd7bbc48,0x3d3ebd2c,0x3bc93d7f,0xbd5cbd04,0x3d353d35,0xbd7d3c16,0x3cf1bd62,0x3cdb3d67,
0xbd35bd35,0x3d803b49,0xbd463d22,0x3c16bd7d,0x3d0e3d55,0xbd78bc79,0x3d62bcf1,0xbcac3d71,0xbcc4bd6d,0x3d673cdb,0xbd753c95,0x3d04bd5c,0x3c483d7b,0xbd4ebd18,0x3d7fbbc9,0xbd2c3d3e,
0xbd800000,0x3d3ebd2c,0xbbc93d7f,0xbd18bd4e,0x3d7b3c48,0xbd5c3d04,0x3c95bd75,0x3cdb3d67,0xbd6dbcc4,0x3d71bcac,0xbcf13d62,0xbc79bd78,0x3d553d0e,0xbd7d3c16,0x3d22bd46,0x3b493d80,
0x3c48bd7b,0x3cac3d71,0xbd46bd22,0x3d7d3c16,0x3d353d35,0xbd78bc79,0x3d75bc95,0xbd2c3d3e,0x3d553d0e,0xbd80bb49,0x3d62bcf1,0xbd043d5c,0xbd6d3cc4,0x3d18bd4e,0xbbc93d7f,0xbcdbbd67,
0x3d0e3d55,0xbd67bcdb,0x3d7fbbc9,0xbd4e3d18,0xbd800000,0x3d5cbd04,0xbcf13d62,0xbb49bd80,0xbd7b3c48,0x3d3ebd2c,0xbc953d75,0xbc79bd78,0x3cc4bd6d,0x3c163d7d,0xbd22bd46,0x3d713cac,
0x3cc43d6d,0xbd2cbd3e,0x3d623cf1,0xbd7dbc16,0x3d7bbc48,0xbd5c3d04,0x3d22bd46,0xbcac3d71,0xbd35bd35,0x3d673cdb,0xbd7fbbc9,0x3d78bc79,0xbd553d0e,0x3d18bd4e,0xbc953d75,0xbb49bd80,
0x3d6d3cc4,0xbd80bb49,0x3d75bc95,0xbd4e3d18,0x3d0ebd55,0xbc793d78,0xbbc9bd7f,0x3cdb3d67,0xbd800000,0x3d71bcac,0xbd463d22,0x3d04bd5c,0xbc483d7b,0xbc16bd7d,0x3cf13d62,0xbd3ebd2c,
0x3d0ebd55,0xbcdb3d67,0x3c95bd75,0xbc163d7d,0x3d6dbcc4,0xbd5c3d04,0x3d46bd22,0xbd2c3d3e,0x3d7b3c48,0xbd80bb49,0x3d7fbbc9,0xbd783c79,0x3d353d35,0xbd4ebd18,0x3d623cf1,0xbd71bcac,
0x3c483d7b,0xbcacbd71,0x3cf13d62,0xbd18bd4e,0xbcc43d6d,0x3c79bd78,0xbbc93d7f,0xbb49bd80,0xbd553d0e,0x3d3ebd2c,0xbd223d46,0x3d04bd5c,0xbd800000,0x3d7dbc16,0xbd753c95,0x3d67bcdb,
0x3d80,0x3b49bd80,0xbbc93d7f,0x3c16bd7d,0xbc483d7b,0x3c79bd78,0xbc953d75,0x3cacbd71,0xbcc43d6d,0x3cdbbd67,0xbcf13d62,0x3d04bd5c,0xbd0e3d55,0x3d18bd4e,0xbd223d46,0x3d2cbd3e,
0xbd353d35,0x3d3ebd2c,0xbd463d22,0x3d4ebd18,0xbd553d0e,0x3d5cbd04,0xbd623cf1,0x3d67bcdb,0xbd6d3cc4,0x3d71bcac,0xbd753c95,0x3d78bc79,0xbd7b3c48,0x3d7dbc16,0xbd7f3bc9,0x3d80bb49,
0xbd553d0e,0x3d71bcac,0xbd7f3bc9,0x3d7d3c16,0x3d80,0x3c79bd78,0xbcf13d62,0x3d2cbd3e,0xbc48bd7b,0xbb493d80,0x3c95bd75,0xbd043d5c,0xbd6dbcc4,0x3d4e3d18,0xbd22bd46,0x3cdb3d67,
0x3d7b3c48,0xbd67bcdb,0x3d463d22,0xbd18bd4e,0x3d35bd35,0xbd5c3d04,0x3d75bc95,0xbd803b49,0xbd0e3d55,0x3d3ebd2c,0xbd623cf1,0x3d78bc79,0x3cc43d6d,0xbc16bd7d,0xbbc93d7f,0x3cacbd71,
0x3cc4bd6d,0xbd3e3d2c,0x3d75bc95,0xbd7dbc16,0x3d553d0e,0xbd04bd5c,0x3bc93d7f,0x3cacbd71,0x3d80,0x3cdbbd67,0xbd463d22,0x3d78bc79,0xbd7bbc48,0x3d4e3d18,0xbcf1bd62,0x3b493d80,
0x3d6dbcc4,0xbd80bb49,0x3d623cf1,0xbd18bd4e,0x3c483d7b,0x3c79bd78,0xbd223d46,0x3d67bcdb,0xbd353d35,0x3d71bcac,0xbd7fbbc9,0x3d5c3d04,0xbd0ebd55,0x3c163d7d,0x3c95bd75,0xbd2c3d3e,
0xbd7b3c48,0x3d673cdb,0xbcf1bd62,0xbc163d7d,0x3d6d3cc4,0xbd04bd5c,0xbbc93d7f,0x3d2cbd3e,0xbd0ebd55,0xbb493d80,0x3d22bd46,0xbd783c79,0x3d80,0x3d18bd4e,0xbd753c95,0x3d713cac,
0x3d553d0e,0xbcacbd71,0xbc953d75,0x3d4ebd18,0xbcc4bd6d,0xbc793d78,0x3d46bd22,0xbd803b49,0xbc483d7b,0x3d3ebd2c,0xbd7f3bc9,0x3d5c3d04,0x3d35bd35,0xbd7d3c16,0x3d623cf1,0xbcdbbd67,
0xbd353d35,0x3d803b49,0xbd22bd46,0xbc163d7d,0x3d55bd0e,0xbd78bc79,0x3cf13d62,0x3cacbd71,0xbd6d3cc4,0x3d673cdb,0xbc95bd75,0xbd043d5c,0x3d7bbc48,0xbd4ebd18,0x3bc93d7f,0x3d2cbd3e,
0x3d80,0x3d3ebd2c,0xbd7fbbc9,0x3d183d4e,0x3c48bd7b,0xbd5c3d04,0x3d753c95,0xbcdbbd67,0xbcc43d6d,0x3d71bcac,0xbd62bcf1,0x3c793d78,0x3d0ebd55,0xbd7d3c16,0x3d463d22,0xbb49bd80,
0xbd7bbc48,0x3cac3d71,0x3d22bd46,0xbd7dbc16,0x3d35bd35,0xbd78bc79,0x3c953d75,0x3d2cbd3e,0x3d0ebd55,0xbd80bb49,0x3cf13d62,0x3d04bd5c,0x3cc43d6d,0x3d18bd4e,0xbd7fbbc9,0x3cdb3d67,
0x3d55bd0e,0xbd67bcdb,0x3bc93d7f,0x3d4ebd18,0x3d80,0x3d5cbd04,0xbd62bcf1,0x3b493d80,0x3c483d7b,0x3d3ebd2c,0xbd75bc95,0x3c793d78,0xbd6dbcc4,0x3c163d7d,0x3d46bd22,0xbd71bcac,
0x3d6dbcc4,0xbd2cbd3e,0xbcf13d62,0x3d7d3c16,0xbc48bd7b,0xbd5c3d04,0x3d463d22,0x3cacbd71,0xbd353d35,0x3d673cdb,0x3bc9bd7f,0xbd783c79,0x3d0e3d55,0x3d18bd4e,0xbd75bc95,0x3b493d80,
0x3cc4bd6d,0xbd80bb49,0x3c953d75,0x3d4ebd18,0xbd55bd0e,0xbc793d78,0x3d7fbbc9,0xbcdbbd67,0x3d80,0x3d71bcac,0xbd22bd46,0xbd043d5c,0x3d7b3c48,0xbc16bd7d,0xbd623cf1,0x3d3e3d2c,
0xbd55bd0e,0xbcdb3d67,0x3d753c95,0x3c16bd7d,0xbcc4bd6d,0xbd5c3d04,0x3d223d46,0x3d2cbd3e,0x3c48bd7b,0xbd80bb49,0x3bc93d7f,0x3d78bc79,0x3d35bd35,0xbd4ebd18,0xbcf13d62,0x3d713cac,
0x3d7bbc48,0xbcacbd71,0xbd623cf1,0x3d183d4e,0x3d6d3cc4,0x3c79bd78,0xbd7fbbc9,0x3b493d80,0x3d0e3d55,0x3d3ebd2c,0xbd46bd22,0xbd043d5c,0x3d80,0x3d7dbc16,0xbc95bd75,0xbd673cdb,
0xbd800000,0x3d803b49,0xbd7fbbc9,0x3d7d3c16,0xbd7bbc48,0x3d783c79,0xbd75bc95,0x3d713cac,0xbd6dbcc4,0x3d673cdb,0xbd62bcf1,0x3d5c3d04,0xbd55bd0e,0x3d4e3d18,0xbd46bd22,0x3d3e3d2c,
0xbd35bd35,0x3d2c3d3e,0xbd22bd46,0x3d183d4e,0xbd0ebd55,0x3d043d5c,0xbcf1bd62,0x3cdb3d67,0xbcc4bd6d,0x3cac3d71,0xbc95bd75,0x3c793d78,0xbc48bd7b,0x3c163d7d,0xbbc9bd7f,0x3b493d80,
0xbd0ebd55,0x3cac3d71,0xbbc9bd7f,0xbc163d7d,0xbd800000,0x3d783c79,0xbd62bcf1,0x3d3e3d2c,0x3d7bbc48,0xbd80bb49,0x3d753c95,0xbd5cbd04,0x3cc4bd6d,0xbd183d4e,0x3d46bd22,0xbd673cdb,
0xbc483d7b,0x3cdbbd67,0xbd223d46,0x3d4ebd18,0x3d353d35,0xbd04bd5c,0x3c953d75,0xbb49bd80,0xbd55bd0e,0x3d2c3d3e,0xbcf1bd62,0x3c793d78,0xbd6d3cc4,0x3d7dbc16,0xbd7fbbc9,0x3d713cac,
0x3d6d3cc4,0xbd2cbd3e,0x3c953d75,0x3c16bd7d,0xbd0e3d55,0x3d5cbd04,0xbd7f3bc9,0x3d713cac,0xbd800000,0x3d673cdb,0xbd22bd46,0x3c793d78,0x3c48bd7b,0xbd183d4e,0x3d62bcf1,0xbd803b49,
0x3cc43d6d,0x3b49bd80,0xbcf13d62,0x3d4ebd18,0xbd7b3c48,0x3d783c79,0xbd46bd22,0x3cdb3d67,0xbd35bd35,0x3cac3d71,0x3bc9bd7f,0xbd043d5c,0x3d55bd0e,0xbd7d3c16,0x3d753c95,0xbd3ebd2c,
0xbc48bd7b,0xbcdb3d67,0x3d62bcf1,0xbd7dbc16,0xbcc43d6d,0x3d5cbd04,0xbd7fbbc9,0x3d3e3d2c,0x3d55bd0e,0xbd80bb49,0x3d463d22,0xbc79bd78,0xbd800000,0x3d4e3d18,0xbc95bd75,0xbcac3d71,
0xbd0e3d55,0x3d71bcac,0xbd75bc95,0x3d183d4e,0x3d6dbcc4,0xbd78bc79,0x3d223d46,0xbb49bd80,0xbd7bbc48,0x3d2c3d3e,0xbbc9bd7f,0xbd043d5c,0x3d353d35,0xbc16bd7d,0xbcf13d62,0x3d67bcdb,
0xbd35bd35,0xbb493d80,0x3d46bd22,0xbd7dbc16,0x3d0e3d55,0x3c79bd78,0xbd623cf1,0x3d713cac,0xbcc4bd6d,0xbcdb3d67,0x3d75bc95,0xbd5cbd04,0x3c483d7b,0x3d18bd4e,0xbd7f3bc9,0x3d3e3d2c,
0xbd800000,0x3d2c3d3e,0x3bc9bd7f,0xbd4e3d18,0x3d7b3c48,0xbd04bd5c,0xbc953d75,0x3d67bcdb,0xbd6dbcc4,0x3cac3d71,0x3cf1bd62,0xbd783c79,0x3d553d0e,0xbc16bd7d,0xbd223d46,0x3d80bb49,
0x3c48bd7b,0xbd713cac,0x3d463d22,0x3c16bd7d,0x3d353d35,0x3c79bd78,0xbd753c95,0x3d3e3d2c,0x3d553d0e,0x3b49bd80,0xbd623cf1,0x3d5c3d04,0xbd6d3cc4,0x3d4e3d18,0x3bc9bd7f,0xbd673cdb,
0x3d0e3d55,0x3cdbbd67,0xbd7f3bc9,0x3d183d4e,0xbd800000,0x3d043d5c,0x3cf1bd62,0xbd803b49,0xbd7b3c48,0x3d2c3d3e,0x3c95bd75,0xbd783c79,0x3cc4bd6d,0xbd7d3c16,0x3d223d46,0x3cacbd71,
0x3cc43d6d,0x3d3ebd2c,0xbd62bcf1,0xbc163d7d,0x3d7bbc48,0xbd04bd5c,0xbd223d46,0x3d713cac,0xbd35bd35,0xbcdb3d67,0x3d7f3bc9,0xbc79bd78,0xbd553d0e,0x3d4e3d18,0x3c95bd75,0xbd803b49,
0x3d6d3cc4,0x3b49bd80,0xbd753c95,0x3d183d4e,0x3d0ebd55,0xbd78bc79,0x3bc93d7f,0x3d67bcdb,0xbd800000,0x3cac3d71,0x3d46bd22,0xbd5cbd04,0xbc483d7b,0x3d7dbc16,0xbcf1bd62,0xbd2c3d3e,
0x3d0ebd55,0xbd67bcdb,0xbc953d75,0x3d7d3c16,0x3d6dbcc4,0xbd04bd5c,0xbd463d22,0x3d3e3d2c,0x3d7b3c48,0x3b49bd80,0xbd7f3bc9,0x3c793d78,0x3d353d35,0x3d18bd4e,0xbd62bcf1,0xbcac3d71,
0x3c483d7b,0x3d71bcac,0xbcf1bd62,0xbd4e3d18,0xbcc43d6d,0x3d783c79,0x3bc9bd7f,0xbd803b49,0xbd553d0e,0x3d2c3d3e,0x3d22bd46,0xbd5cbd04,0xbd800000,0x3c163d7d,0x3d75bc95,0xbcdbbd67,
0x3d80,0x3d803b49,0x3bc9bd7f,0xbd7dbc16,0xbc483d7b,0x3d783c79,0x3c95bd75,0xbd71bcac,0xbcc43d6d,0x3d673cdb,0x3cf1bd62,0xbd5cbd04,0xbd0e3d55,0x3d4e3d18,0x3d22bd46,0xbd3ebd2c,
0xbd353d35,0x3d2c3d3e,0x3d46bd22,0xbd18bd4e,0xbd553d0e,0x3d043d5c,0x3d62bcf1,0xbcdbbd67,0xbd6d3cc4,0x3cac3d71,0x3d75bc95,0xbc79bd78,0xbd7b3c48,0x3c163d7d,0x3d7fbbc9,0xbb49bd80,
0xbd553d0e,0x3cac3d71,0x3d7fbbc9,0x3c16bd7d,0x3d80,0x3d783c79,0x3cf1bd62,0xbd3ebd2c,0xbc48bd7b,0xbd80bb49,0xbc953d75,0x3d5c3d04,0xbd6dbcc4,0xbd183d4e,0x3d223d46,0x3d67bcdb,
0x3d7b3c48,0x3cdbbd67,0xbd46bd22,0xbd4e3d18,0x3d35bd35,0xbd04bd5c,0xbd753c95,0x3b493d80,0xbd0e3d55,0x3d2c3d3e,0x3d62bcf1,0xbc79bd78,0x3cc43d6d,0x3d7dbc16,0x3bc9bd7f,0xbd71bcac,
0x3cc4bd6d,0xbd2cbd3e,0xbd753c95,0xbc163d7d,0x3d553d0e,0x3d5cbd04,0xbbc9bd7f,0xbd71bcac,0x3d80,0x3d673cdb,0x3d46bd22,0xbc79bd78,0xbd7bbc48,0xbd183d4e,0x3cf13d62,0x3d80bb49,
0x3d6dbcc4,0x3b49bd80,0xbd62bcf1,0xbd4e3d18,0x3c483d7b,0x3d783c79,0x3d22bd46,0xbcdbbd67,0xbd353d35,0x3cac3d71,0x3d7f3bc9,0x3d04bd5c,0xbd0ebd55,0xbd7d3c16,0xbc953d75,0x3d3e3d2c,
0xbd7b3c48,0xbcdb3d67,0x3cf13d62,0x3d7d3c16,0x3d6d3cc4,0x3d5cbd04,0x3bc9bd7f,0xbd3ebd2c,0xbd0ebd55,0xbd80bb49,0xbd223d46,0x3c793d78,0x3d80,0x3d4e3d18,0x3d75bc95,0x3cacbd71,
0x3d553d0e,0x3d71bcac,0x3c95bd75,0xbd18bd4e,0xbcc4bd6d,0xbd78bc79,0xbd463d22,0x3b493d80,0xbc483d7b,0x3d2c3d3e,0x3d7fbbc9,0x3d04bd5c,0x3d35bd35,0xbc16bd7d,0xbd62bcf1,0xbd673cdb,
0xbd353d35,0xbb493d80,0x3d223d46,0x3d7d3c16,0x3d55bd0e,0x3c79bd78,0xbcf1bd62,0xbd71bcac,0xbd6d3cc4,0xbcdb3d67,0x3c953d75,0x3d5c3d04,0x3d7bbc48,0x3d18bd4e,0xbbc9bd7f,0xbd3ebd2c,
0x3d80,0x3d2c3d3e,0x3d7f3bc9,0x3d4ebd18,0x3c48bd7b,0xbd04bd5c,0xbd75bc95,0xbd673cdb,0xbcc43d6d,0x3cac3d71,0x3d623cf1,0x3d78bc79,0x3d0ebd55,0xbc16bd7d,0xbd46bd22,0xbd803b49,
0xbd7bbc48,0xbd713cac,0xbd223d46,0xbc163d7d,0x3d35bd35,0x3c79bd78,0xbc95bd75,0xbd3ebd2c,0x3d0ebd55,0x3b49bd80,0xbcf1bd62,0xbd5cbd04,0x3cc43d6d,0x3d4e3d18,0x3d7f3bc9,0x3d67bcdb,
0x3d55bd0e,0x3cdbbd67,0xbbc9bd7f,0xbd18bd4e,0x3d80,0x3d043d5c,0x3d623cf1,0x3d80bb49,0x3c483d7b,0x3d2c3d3e,0x3d753c95,0x3d78bc79,0xbd6dbcc4,0xbd7d3c16,0xbd463d22,0xbcac3d71,
0x3d6dbcc4,0x3d3ebd2c,0x3cf1bd62,0x3c16bd7d,0xbc48bd7b,0xbd04bd5c,0xbd46bd22,0xbd71bcac,0xbd353d35,0xbcdb3d67,0xbbc93d7f,0x3c793d78,0x3d0e3d55,0x3d4e3d18,0x3d753c95,0x3d80bb49,
0x3cc4bd6d,0x3b49bd80,0xbc95bd75,0xbd18bd4e,0xbd55bd0e,0xbd78bc79,0xbd7f3bc9,0xbd673cdb,0x3d80,0x3cac3d71,0x3d223d46,0x3d5c3d04,0x3d7b3c48,0x3d7dbc16,0x3d62bcf1,0x3d2cbd3e,
0xbd55bd0e,0xbd67bcdb,0xbd75bc95,0xbd7dbc16,0xbcc4bd6d,0xbd04bd5c,0xbd22bd46,0xbd3ebd2c,0x3c48bd7b,0x3b49bd80,0xbbc9bd7f,0xbc79bd78,0x3d35bd35,0x3d18bd4e,0x3cf1bd62,0x3cacbd71,
0x3d7bbc48,0x3d71bcac,0x3d62bcf1,0x3d4ebd18,0x3d6d3cc4,0x3d783c79,0x3d7f3bc9,0x3d80bb49,0x3d0e3d55,0x3d2c3d3e,0x3d463d22,0x3d5c3d04,0x3d80,0x3c163d7d,0x3c953d75,0x3cdb3d67,
0xbd800000,0xbb493d80,0x3d7f3bc9,0x3c16bd7d,0xbd7bbc48,0xbc793d78,0x3d753c95,0x3cacbd71,0xbd6dbcc4,0xbcdb3d67,0x3d623cf1,0x3d04bd5c,0xbd55bd0e,0xbd183d4e,0x3d463d22,0x3d2cbd3e,
0xbd35bd35,0xbd3e3d2c,0x3d223d46,0x3d4ebd18,0xbd0ebd55,0xbd5c3d04,0x3cf13d62,0x3d67bcdb,0xbcc4bd6d,0xbd713cac,0x3c953d75,0x3d78bc79,0xbc48bd7b,0xbd7d3c16,0x3bc93d7f,0x3d80bb49,
0xbd0ebd55,0xbd713cac,0x3bc93d7f,0x3d7d3c16,0xbd800000,0xbc793d78,0x3d623cf1,0x3d2cbd3e,0x3d7bbc48,0x3b49bd80,0xbd75bc95,0xbd043d5c,0x3cc4bd6d,0xbd4ebd18,0xbd463d22,0x3cdb3d67,
0xbc483d7b,0x3d673cdb,0x3d22bd46,0xbd18bd4e,0x3d353d35,0x3d5cbd04,0xbc95bd75,0xbd803b49,0xbd55bd0e,0xbd3e3d2c,0x3cf13d62,0x3d78bc79,0xbd6d3cc4,0x3c163d7d,0x3d7f3bc9,0x3cacbd71,
0x3d6d3cc4,0x3d3ebd2c,0xbc95bd75,0xbd7dbc16,0xbd0e3d55,0x3d043d5c,0x3d7fbbc9,0x3cacbd71,0xbd800000,0xbcdb3d67,0x3d223d46,0x3d78bc79,0x3c48bd7b,0xbd4ebd18,0xbd623cf1,0x3b493d80,
0x3cc43d6d,0x3d803b49,0x3cf1bd62,0xbd18bd4e,0xbd7b3c48,0xbc793d78,0x3d463d22,0x3d67bcdb,0xbd35bd35,0xbd713cac,0xbbc93d7f,0x3d5c3d04,0x3d55bd0e,0xbc16bd7d,0xbd75bc95,0xbd2c3d3e,
0xbc48bd7b,0xbd67bcdb,0xbd623cf1,0xbc163d7d,0xbcc43d6d,0x3d043d5c,0x3d7f3bc9,0x3d2cbd3e,0x3d55bd0e,0x3b49bd80,0xbd46bd22,0xbd783c79,0xbd800000,0xbd183d4e,0x3c953d75,0x3d713cac,
0xbd0e3d55,0x3cac3d71,0x3d753c95,0x3d4ebd18,0x3d6dbcc4,0x3c79bd78,0xbd22bd46,0xbd803b49,0xbd7bbc48,0xbd3e3d2c,0x3bc93d7f,0x3d5c3d04,0x3d353d35,0x3d7dbc16,0x3cf1bd62,0xbcdbbd67,
0xbd35bd35,0xbd80bb49,0xbd463d22,0xbc163d7d,0x3d0e3d55,0x3d783c79,0x3d62bcf1,0x3cacbd71,0xbcc4bd6d,0xbd67bcdb,0xbd753c95,0xbd043d5c,0x3c483d7b,0x3d4e3d18,0x3d7fbbc9,0x3d2cbd3e,
0xbd800000,0xbd3e3d2c,0xbbc93d7f,0x3d183d4e,0x3d7b3c48,0x3d5cbd04,0x3c95bd75,0xbcdbbd67,0xbd6dbcc4,0xbd713cac,0xbcf13d62,0x3c793d78,0x3d553d0e,0x3d7dbc16,0x3d22bd46,0xbb49bd80,
0x3c48bd7b,0xbcacbd71,0xbd46bd22,0xbd7dbc16,0x3d353d35,0x3d783c79,0x3d75bc95,0x3d2cbd3e,0x3d553d0e,0x3d803b49,0x3d62bcf1,0x3d04bd5c,0xbd6d3cc4,0xbd183d4e,0xbbc93d7f,0x3cdb3d67,
0x3d0e3d55,0x3d673cdb,0x3d7fbbc9,0x3d4ebd18,0xbd800000,0xbd5c3d04,0xbcf13d62,0x3b493d80,0xbd7b3c48,0xbd3e3d2c,0xbc953d75,0x3c793d78,0x3cc4bd6d,0xbc16bd7d,0xbd22bd46,0xbd71bcac,
0x3cc43d6d,0x3d2c3d3e,0x3d623cf1,0x3d7d3c16,0x3d7bbc48,0x3d5cbd04,0x3d22bd46,0x3cacbd71,0xbd35bd35,0xbd67bcdb,0xbd7fbbc9,0xbd783c79,0xbd553d0e,0xbd183d4e,0xbc953d75,0x3b493d80,
0x3d6d3cc4,0x3d803b49,0x3d75bc95,0x3d4ebd18,0x3d0ebd55,0x3c79bd78,0xbbc9bd7f,0xbcdbbd67,0xbd800000,0xbd713cac,0xbd463d22,0xbd043d5c,0xbc483d7b,0x3c163d7d,0x3cf13d62,0x3d3e3d2c,
0x3d0ebd55,0x3cdbbd67,0x3c95bd75,0x3c16bd7d,0x3d6dbcc4,0x3d5cbd04,0x3d46bd22,0x3d2cbd3e,0x3d7b3c48,0x3d803b49,0x3d7fbbc9,0x3d78bc79,0x3d353d35,0x3d4e3d18,0x3d623cf1,0x3d713cac,
0x3c483d7b,0x3cac3d71,0x3cf13d62,0x3d183d4e,0xbcc43d6d,0xbc793d78,0xbbc93d7f,0x3b493d80,0xbd553d0e,0xbd3e3d2c,0xbd223d46,0xbd043d5c,0xbd800000,0xbd7d3c16,0xbd753c95,0xbd673cdb,
0x3d80,0xbbc93d7f,0xbc483d7b,0xbc953d75,0xbcc43d6d,0xbcf13d62,0xbd0e3d55,0xbd223d46,0xbd353d35,0xbd463d22,0xbd553d0e,0xbd623cf1,0xbd6d3cc4,0xbd753c95,0xbd7b3c48,0xbd7f3bc9,
0xbd800000,0xbd7fbbc9,0xbd7bbc48,0xbd75bc95,0xbd6dbcc4,0xbd62bcf1,0xbd55bd0e,0xbd46bd22,0xbd35bd35,0xbd22bd46,0xbd0ebd55,0xbcf1bd62,0xbcc4bd6d,0xbc95bd75,0xbc48bd7b,0xbbc9bd7f,
0xbd6d3cc4,0xbd7f3bc9,0xbd7bbc48,0xbd62bcf1,0x3d80,0xbc953d75,0xbd0e3d55,0xbd463d22,0x3cc4bd6d,0x3d22bd46,0x3d55bd0e,0x3d75bc95,0xbd35bd35,0xbcf1bd62,0xbc48bd7b,0x3bc9bd7f,
0x3cc43d6d,0x3bc93d7f,0xbc483d7b,0xbcf13d62,0x3d800000,0x3d753c95,0x3d553d0e,0x3d223d46,0xbd6dbcc4,0xbd46bd22,0xbd0ebd55,0xbc95bd75,0xbd353d35,0xbd623cf1,0xbd7b3c48,0xbd7fbbc9,
0x3d35bd35,0x3d75bc95,0x3d7b3c48,0x3d463d22,0x3cc43d6d,0xbbc93d7f,0xbd0e3d55,0xbd623cf1,0x3d80,0xbcf13d62,0xbd553d0e,0xbd7f3bc9,0xbd6dbcc4,0xbd22bd46,0xbc48bd7b,0x3c95bd75,
0x3d353d35,0x3c953d75,0xbc483d7b,0xbd223d46,0xbd6d3cc4,0xbd7fbbc9,0xbd55bd0e,0xbcf1bd62,0xbd800000,0xbd62bcf1,0xbd0ebd55,0xbbc9bd7f,0x3cc4bd6d,0x3d46bd22,0x3d7bbc48,0x3d753c95,
0xbd6dbcc4,0xbcf1bd62,0x3c48bd7b,0x3d46bd22,0x3d353d35,0x3bc93d7f,0xbd0e3d55,0xbd753c95,0xbcc4bd6d,0x3c95bd75,0x3d55bd0e,0x3d7f3bc9,0x3d80,0xbd223d46,0xbd7b3c48,0xbd62bcf1,
0xbcc43d6d,0xbd623cf1,0xbd7bbc48,0xbd22bd46,0x3d35bd35,0x3d7fbbc9,0x3d553d0e,0x3c953d75,0xbd6d3cc4,0xbd75bc95,0xbd0ebd55,0x3bc9bd7f,0x3d800000,0x3d463d22,0x3c483d7b,0xbcf13d62,
0xbd800000,0xbd22bd46,0x3c48bd7b,0x3d62bcf1,0x3d6d3cc4,0x3c953d75,0xbd0e3d55,0xbd7f3bc9,0xbd35bd35,0x3bc9bd7f,0x3d55bd0e,0x3d753c95,0x3cc43d6d,0xbcf13d62,0xbd7b3c48,0xbd46bd22,
0x3d80,0xbd463d22,0xbd7bbc48,0xbcf1bd62,0x3cc4bd6d,0x3d75bc95,0x3d553d0e,0x3bc93d7f,0xbd353d35,0xbd7fbbc9,0xbd0ebd55,0x3c95bd75,0x3d6dbcc4,0x3d623cf1,0x3c483d7b,0xbd223d46,
0xbcc4bd6d,0x3d22bd46,0x3d7b3c48,0x3c953d75,0x3d800000,0x3cf13d62,0xbd0e3d55,0xbd7fbbc9,0x3d6d3cc4,0x3bc93d7f,0xbd553d0e,0xbd62bcf1,0xbd353d35,0xbd75bc95,0xbc48bd7b,0x3d46bd22,
0x3d6dbcc4,0x3d463d22,0xbc483d7b,0xbd753c95,0x3d80,0xbd623cf1,0xbd55bd0e,0x3bc9bd7f,0xbcc43d6d,0xbd7f3bc9,0xbd0ebd55,0x3cf1bd62,0xbd35bd35,0x3c95bd75,0x3d7bbc48,0x3d223d46,
0x3d353d35,0xbcf13d62,0xbd7bbc48,0xbbc9bd7f,0x3d6dbcc4,0x3d223d46,0xbd0e3d55,0xbd75bc95,0xbd800000,0xbc95bd75,0x3d55bd0e,0x3d463d22,0xbcc43d6d,0xbd7fbbc9,0xbc48bd7b,0x3d62bcf1,
0x3d35bd35,0x3d623cf1,0xbc483d7b,0xbd7f3bc9,0xbcc4bd6d,0x3d46bd22,0x3d553d0e,0xbc953d75,0x3d80,0xbd753c95,0xbd0ebd55,0x3d22bd46,0x3d6d3cc4,0xbbc93d7f,0xbd7b3c48,0xbcf1bd62,
0x3cc4bd6d,0x3d753c95,0xbc483d7b,0xbd7fbbc9,0x3d35bd35,0x3d463d22,0xbd0e3d55,0xbd62bcf1,0x3d6dbcc4,0x3cf13d62,0xbd553d0e,0xbd22bd46,0x3d800000,0x3bc93d7f,0xbd7b3c48,0xbc95bd75,
0x3d6d3cc4,0xbc953d75,0xbd7bbc48,0x3bc9bd7f,0x3d353d35,0xbd223d46,0xbd55bd0e,0x3cf1bd62,0x3cc43d6d,0xbd623cf1,0xbd0ebd55,0x3d46bd22,0x3d80,0xbd7f3bc9,0xbc48bd7b,0x3d75bc95,
0xbd800000,0xbd7fbbc9,0xbd7bbc48,0xbd75bc95,0xbd6dbcc4,0xbd62bcf1,0xbd55bd0e,0xbd46bd22,0xbd35bd35,0xbd22bd46,0xbd0ebd55,0xbcf1bd62,0xbcc4bd6d,0xbc95bd75,0xbc48bd7b,0xbbc9bd7f,
0x8000bd80,0x3bc9bd7f,0x3c48bd7b,0x3c95bd75,0x3cc4bd6d,0x3cf1bd62,0x3d0ebd55,0x3d22bd46,0x3d35bd35,0x3d46bd22,0x3d55bd0e,0x3d62bcf1,0x3d6dbcc4,0x3d75bc95,0x3d7bbc48,0x3d7fbbc9,
0xbcc4bd6d,0xbbc9bd7f,0x3c48bd7b,0x3cf1bd62,0xbd800000,0xbd75bc95,0xbd55bd0e,0xbd22bd46,0x3d6d3cc4,0x3d463d22,0x3d0e3d55,0x3c953d75,0x3d35bd35,0x3d62bcf1,0x3d7bbc48,0x3d7f3bc9,
0xbd6d3cc4,0xbd7f3bc9,0xbd7bbc48,0xbd62bcf1,0x80003d80,0xbc953d75,0xbd0e3d55,0xbd463d22,0x3cc4bd6d,0x3d22bd46,0x3d55bd0e,0x3d75bc95,0xbd35bd35,0xbcf1bd62,0xbc48bd7b,0x3bc9bd7f,
0x3d353d35,0x3c953d75,0xbc483d7b,0xbd223d46,0xbd6d3cc4,0xbd7fbbc9,0xbd55bd0e,0xbcf1bd62,0xbd800000,0xbd62bcf1,0xbd0ebd55,0xbbc9bd7f,0x3cc4bd6d,0x3d46bd22,0x3d7bbc48,0x3d753c95,
0xbd353d35,0xbd753c95,0xbd7bbc48,0xbd46bd22,0xbcc4bd6d,0x3bc9bd7f,0x3d0ebd55,0x3d62bcf1,0x8000bd80,0x3cf1bd62,0x3d55bd0e,0x3d7fbbc9,0x3d6d3cc4,0x3d223d46,0x3c483d7b,0xbc953d75,
0x3cc4bd6d,0x3d62bcf1,0x3d7b3c48,0x3d223d46,0xbd353d35,0xbd7f3bc9,0xbd55bd0e,0xbc95bd75,0x3d6dbcc4,0x3d753c95,0x3d0e3d55,0xbbc93d7f,0xbd800000,0xbd46bd22,0xbc48bd7b,0x3cf1bd62,
0xbd6dbcc4,0xbcf1bd62,0x3c48bd7b,0x3d46bd22,0x3d353d35,0x3bc93d7f,0xbd0e3d55,0xbd753c95,0xbcc4bd6d,0x3c95bd75,0x3d55bd0e,0x3d7f3bc9,0x80003d80,0xbd223d46,0xbd7b3c48,0xbd62bcf1,
0x8000bd80,0x3d46bd22,0x3d7b3c48,0x3cf13d62,0xbcc43d6d,0xbd753c95,0xbd55bd0e,0xbbc9bd7f,0x3d35bd35,0x3d7f3bc9,0x3d0e3d55,0xbc953d75,0xbd6d3cc4,0xbd62bcf1,0xbc48bd7b,0x3d22bd46,
0xbd800000,0xbd22bd46,0x3c48bd7b,0x3d62bcf1,0x3d6d3cc4,0x3c953d75,0xbd0e3d55,0xbd7f3bc9,0xbd35bd35,0x3bc9bd7f,0x3d55bd0e,0x3d753c95,0x3cc43d6d,0xbcf13d62,0xbd7b3c48,0xbd46bd22,
0x3d6dbcc4,0x3d463d22,0xbc483d7b,0xbd753c95,0x80003d80,0xbd623cf1,0xbd55bd0e,0x3bc9bd7f,0xbcc43d6d,0xbd7f3bc9,0xbd0ebd55,0x3cf1bd62,0xbd35bd35,0x3c95bd75,0x3d7bbc48,0x3d223d46,
0x3cc43d6d,0xbd223d46,0xbd7bbc48,0xbc95bd75,0xbd800000,0xbcf1bd62,0x3d0ebd55,0x3d7f3bc9,0xbd6dbcc4,0xbbc9bd7f,0x3d55bd0e,0x3d623cf1,0x3d35bd35,0x3d753c95,0x3c483d7b,0xbd463d22,
0xbd353d35,0xbd62bcf1,0x3c48bd7b,0x3d7fbbc9,0x3cc43d6d,0xbd463d22,0xbd55bd0e,0x3c95bd75,0x8000bd80,0x3d75bc95,0x3d0e3d55,0xbd223d46,0xbd6dbcc4,0x3bc9bd7f,0x3d7bbc48,0x3cf13d62,
0x3d353d35,0xbcf13d62,0xbd7bbc48,0xbbc9bd7f,0x3d6dbcc4,0x3d223d46,0xbd0e3d55,0xbd75bc95,0xbd800000,0xbc95bd75,0x3d55bd0e,0x3d463d22,0xbcc43d6d,0xbd7fbbc9,0xbc48bd7b,0x3d62bcf1,
0x3d6d3cc4,0xbc953d75,0xbd7bbc48,0x3bc9bd7f,0x3d353d35,0xbd223d46,0xbd55bd0e,0x3cf1bd62,0x3cc43d6d,0xbd623cf1,0xbd0ebd55,0x3d46bd22,0x80003d80,0xbd7f3bc9,0xbc48bd7b,0x3d75bc95,
0xbcc43d6d,0xbd75bc95,0x3c48bd7b,0x3d7f3bc9,0xbd353d35,0xbd46bd22,0x3d0ebd55,0x3d623cf1,0xbd6d3cc4,0xbcf1bd62,0x3d55bd0e,0x3d223d46,0xbd800000,0xbbc9bd7f,0x3d7bbc48,0x3c953d75,
0x3d80,0xbd7fbbc9,0x3c48bd7b,0x3d753c95,0xbcc43d6d,0xbd62bcf1,0x3d0ebd55,0x3d463d22,0xbd353d35,0xbd22bd46,0x3d55bd0e,0x3cf13d62,0xbd6d3cc4,0xbc95bd75,0x3d7bbc48,0x3bc93d7f,
0xbd800000,0x3bc9bd7f,0x3d7b3c48,0xbc953d75,0xbd6dbcc4,0x3cf1bd62,0x3d553d0e,0xbd223d46,0xbd35bd35,0x3d46bd22,0x3d0e3d55,0xbd623cf1,0xbcc4bd6d,0x3d75bc95,0x3c483d7b,0xbd7f3bc9,
0xbd6d3cc4,0xbbc9bd7f,0x3d7b3c48,0xbcf13d62,0x3d80,0xbd75bc95,0x3d0ebd55,0x3d223d46,0x3cc4bd6d,0x3d463d22,0xbd553d0e,0xbc95bd75,0xbd35bd35,0x3d62bcf1,0x3c483d7b,0xbd7fbbc9,
0x3cc43d6d,0xbd7f3bc9,0x3c48bd7b,0x3d623cf1,0x3d800000,0xbc953d75,0xbd55bd0e,0x3d46bd22,0xbd6dbcc4,0x3d22bd46,0x3d0e3d55,0xbd753c95,0xbd353d35,0xbcf1bd62,0x3d7bbc48,0xbbc93d7f,
0x3d35bd35,0x3c953d75,0xbd7bbc48,0x3d22bd46,0x3cc43d6d,0xbd7fbbc9,0x3d0ebd55,0x3cf13d62,0x3d80,0xbd62bcf1,0x3d55bd0e,0x3bc93d7f,0xbd6dbcc4,0x3d46bd22,0x3c483d7b,0xbd75bc95,
0x3d353d35,0xbd753c95,0x3c48bd7b,0x3d463d22,0xbd6d3cc4,0x3bc9bd7f,0x3d553d0e,0xbd623cf1,0xbd800000,0x3cf1bd62,0x3d0e3d55,0xbd7f3bc9,0x3cc4bd6d,0x3d223d46,0xbd7b3c48,0x3c95bd75,
0xbd6dbcc4,0x3d62bcf1,0xbc483d7b,0xbd22bd46,0x3d353d35,0xbd7f3bc9,0x3d0ebd55,0x3c953d75,0xbcc4bd6d,0x3d753c95,0xbd553d0e,0x3bc9bd7f,0x3d80,0xbd46bd22,0x3d7bbc48,0xbcf13d62,
0xbcc43d6d,0xbcf1bd62,0x3d7b3c48,0xbd463d22,0x3d35bd35,0x3bc93d7f,0xbd55bd0e,0x3d75bc95,0xbd6d3cc4,0x3c95bd75,0x3d0e3d55,0xbd7fbbc9,0x3d800000,0xbd223d46,0xbc48bd7b,0x3d623cf1,
0xbd800000,0x3d46bd22,0xbc483d7b,0xbcf1bd62,0x3d6d3cc4,0xbd753c95,0x3d0ebd55,0x3bc93d7f,0xbd35bd35,0x3d7f3bc9,0xbd553d0e,0x3c95bd75,0x3cc43d6d,0xbd62bcf1,0x3d7bbc48,0xbd223d46,
0x3d80,0xbd22bd46,0x3d7b3c48,0xbd623cf1,0x3cc4bd6d,0x3c953d75,0xbd55bd0e,0x3d7fbbc9,0xbd353d35,0x3bc9bd7f,0x3d0e3d55,0xbd75bc95,0x3d6dbcc4,0xbcf13d62,0xbc48bd7b,0x3d463d22,
0xbcc4bd6d,0x3d463d22,0xbd7bbc48,0x3d75bc95,0x3d800000,0xbd623cf1,0x3d0ebd55,0xbbc93d7f,0x3d6d3cc4,0xbd7f3bc9,0x3d55bd0e,0xbcf13d62,0xbd353d35,0x3c95bd75,0x3c483d7b,0xbd22bd46,
0x3d6dbcc4,0xbd223d46,0x3c48bd7b,0x3c953d75,0x3d80,0xbcf1bd62,0x3d553d0e,0xbd7fbbc9,0xbcc43d6d,0xbbc9bd7f,0x3d0e3d55,0xbd62bcf1,0xbd35bd35,0x3d753c95,0xbd7b3c48,0x3d46bd22,
0x3d353d35,0xbd62bcf1,0x3d7b3c48,0xbd7f3bc9,0x3d6dbcc4,0xbd463d22,0x3d0ebd55,0xbc953d75,0xbd800000,0x3d75bc95,0xbd553d0e,0x3d22bd46,0xbcc43d6d,0x3bc9bd7f,0x3c483d7b,0xbcf1bd62,
0x3d35bd35,0xbcf13d62,0x3c48bd7b,0x3bc93d7f,0xbcc4bd6d,0x3d223d46,0xbd55bd0e,0x3d753c95,0x3d80,0xbc95bd75,0x3d0e3d55,0xbd46bd22,0x3d6d3cc4,0xbd7fbbc9,0x3d7bbc48,0xbd623cf1,
0x3cc4bd6d,0xbc953d75,0x3c48bd7b,0xbbc93d7f,0x3d35bd35,0xbd223d46,0x3d0ebd55,0xbcf13d62,0x3d6dbcc4,0xbd623cf1,0x3d55bd0e,0xbd463d22,0x3d800000,0xbd7f3bc9,0x3d7bbc48,0xbd753c95,
0x3d6d3cc4,0xbd75bc95,0x3d7b3c48,0xbd7fbbc9,0x3d353d35,0xbd46bd22,0x3d553d0e,0xbd62bcf1,0x3cc43d6d,0xbcf1bd62,0x3d0e3d55,0xbd22bd46,0x3d80,0xbbc9bd7f,0x3c483d7b,0xbc95bd75,
0xbd800000,0x3bc9bd7f,0x3d7b3c48,0xbc953d75,0xbd6dbcc4,0x3cf1bd62,0x3d553d0e,0xbd223d46,0xbd35bd35,0x3d46bd22,0x3d0e3d55,0xbd623cf1,0xbcc4bd6d,0x3d75bc95,0x3c483d7b,0xbd7f3bc9,
0x8000bd80,0x3d7f3bc9,0xbc483d7b,0xbd75bc95,0x3cc4bd6d,0x3d623cf1,0xbd0e3d55,0xbd46bd22,0x3d35bd35,0x3d223d46,0xbd553d0e,0xbcf1bd62,0x3d6dbcc4,0x3c953d75,0xbd7b3c48,0xbbc9bd7f,
0xbcc4bd6d,0x3d7fbbc9,0xbc483d7b,0xbd62bcf1,0xbd800000,0x3c95bd75,0x3d553d0e,0xbd463d22,0x3d6d3cc4,0xbd223d46,0xbd0ebd55,0x3d75bc95,0x3d35bd35,0x3cf13d62,0xbd7b3c48,0x3bc9bd7f,
0xbd6d3cc4,0xbbc9bd7f,0x3d7b3c48,0xbcf13d62,0x80003d80,0xbd75bc95,0x3d0ebd55,0x3d223d46,0x3cc4bd6d,0x3d463d22,0xbd553d0e,0xbc95bd75,0xbd35bd35,0x3d62bcf1,0x3c483d7b,0xbd7fbbc9,
0x3d353d35,0xbd753c95,0x3c48bd7b,0x3d463d22,0xbd6d3cc4,0x3bc9bd7f,0x3d553d0e,0xbd623cf1,0xbd800000,0x3cf1bd62,0x3d0e3d55,0xbd7f3bc9,0x3cc4bd6d,0x3d223d46,0xbd7b3c48,0x3c95bd75,
0xbd353d35,0xbc95bd75,0x3d7b3c48,0xbd223d46,0xbcc4bd6d,0x3d7f3bc9,0xbd0e3d55,0xbcf1bd62,0x8000bd80,0x3d623cf1,0xbd553d0e,0xbbc9bd7f,0x3d6d3cc4,0xbd463d22,0xbc48bd7b,0x3d753c95,
0x3cc4bd6d,0x3cf13d62,0xbd7bbc48,0x3d46bd22,0xbd353d35,0xbbc9bd7f,0x3d553d0e,0xbd753c95,0x3d6dbcc4,0xbc953d75,0xbd0ebd55,0x3d7f3bc9,0xbd800000,0x3d22bd46,0x3c483d7b,0xbd62bcf1,
0xbd6dbcc4,0x3d62bcf1,0xbc483d7b,0xbd22bd46,0x3d353d35,0xbd7f3bc9,0x3d0ebd55,0x3c953d75,0xbcc4bd6d,0x3d753c95,0xbd553d0e,0x3bc9bd7f,0x80003d80,0xbd46bd22,0x3d7bbc48,0xbcf13d62,
0x8000bd80,0x3d223d46,0xbd7bbc48,0x3d62bcf1,0xbcc43d6d,0xbc95bd75,0x3d553d0e,0xbd7f3bc9,0x3d35bd35,0xbbc93d7f,0xbd0ebd55,0x3d753c95,0xbd6d3cc4,0x3cf1bd62,0x3c483d7b,0xbd46bd22,
0xbd800000,0x3d46bd22,0xbc483d7b,0xbcf1bd62,0x3d6d3cc4,0xbd753c95,0x3d0ebd55,0x3bc93d7f,0xbd35bd35,0x3d7f3bc9,0xbd553d0e,0x3c95bd75,0x3cc43d6d,0xbd62bcf1,0x3d7bbc48,0xbd223d46,
0x3d6dbcc4,0xbd223d46,0x3c48bd7b,0x3c953d75,0x80003d80,0xbcf1bd62,0x3d553d0e,0xbd7fbbc9,0xbcc43d6d,0xbbc9bd7f,0x3d0e3d55,0xbd62bcf1,0xbd35bd35,0x3d753c95,0xbd7b3c48,0x3d46bd22,
0x3cc43d6d,0xbd46bd22,0x3d7b3c48,0xbd753c95,0xbd800000,0x3d62bcf1,0xbd0e3d55,0x3bc9bd7f,0xbd6dbcc4,0x3d7fbbc9,0xbd553d0e,0x3cf1bd62,0x3d35bd35,0xbc953d75,0xbc48bd7b,0x3d223d46,
0xbd353d35,0x3cf1bd62,0xbc483d7b,0xbbc9bd7f,0x3cc43d6d,0xbd22bd46,0x3d553d0e,0xbd75bc95,0x8000bd80,0x3c953d75,0xbd0ebd55,0x3d463d22,0xbd6dbcc4,0x3d7f3bc9,0xbd7b3c48,0x3d62bcf1,
0x3d353d35,0xbd62bcf1,0x3d7b3c48,0xbd7f3bc9,0x3d6dbcc4,0xbd463d22,0x3d0ebd55,0xbc953d75,0xbd800000,0x3d75bc95,0xbd553d0e,0x3d22bd46,0xbcc43d6d,0x3bc9bd7f,0x3c483d7b,0xbcf1bd62,
0x3d6d3cc4,0xbd75bc95,0x3d7b3c48,0xbd7fbbc9,0x3d353d35,0xbd46bd22,0x3d553d0e,0xbd62bcf1,0x3cc43d6d,0xbcf1bd62,0x3d0e3d55,0xbd22bd46,0x80003d80,0xbbc9bd7f,0x3c483d7b,0xbc95bd75,
0xbcc43d6d,0x3c95bd75,0xbc483d7b,0x3bc9bd7f,0xbd353d35,0x3d22bd46,0xbd0e3d55,0x3cf1bd62,0xbd6d3cc4,0x3d62bcf1,0xbd553d0e,0x3d46bd22,0xbd800000,0x3d7fbbc9,0xbd7b3c48,0x3d75bc95,
0x3d80,0x3bc9bd7f,0xbc483d7b,0x3c95bd75,0xbcc43d6d,0x3cf1bd62,0xbd0e3d55,0x3d22bd46,0xbd353d35,0x3d46bd22,0xbd553d0e,0x3d62bcf1,0xbd6d3cc4,0x3d75bc95,0xbd7b3c48,0x3d7fbbc9,
0xbd800000,0x3d7f3bc9,0xbd7bbc48,0x3d753c95,0xbd6dbcc4,0x3d623cf1,0xbd55bd0e,0x3d463d22,0xbd35bd35,0x3d223d46,0xbd0ebd55,0x3cf13d62,0xbcc4bd6d,0x3c953d75,0xbc48bd7b,0x3bc93d7f,
0xbd6d3cc4,0x3d7fbbc9,0xbd7bbc48,0x3d623cf1,0x3d80,0x3c95bd75,0xbd0e3d55,0x3d46bd22,0x3cc4bd6d,0xbd223d46,0x3d55bd0e,0xbd753c95,0xbd35bd35,0x3cf13d62,0xbc48bd7b,0xbbc93d7f,
0x3cc43d6d,0xbbc9bd7f,0xbc483d7b,0x3cf1bd62,0x3d800000,0xbd75bc95,0x3d553d0e,0xbd22bd46,0xbd6dbcc4,0x3d463d22,0xbd0ebd55,0x3c953d75,0xbd353d35,0x3d62bcf1,0xbd7b3c48,0x3d7f3bc9,
0x3d35bd35,0xbd753c95,0x3d7b3c48,0xbd46bd22,0x3cc43d6d,0x3bc9bd7f,0xbd0e3d55,0x3d62bcf1,0x3d80,0x3cf1bd62,0xbd553d0e,0x3d7fbbc9,0xbd6dbcc4,0x3d223d46,0xbc48bd7b,0xbc953d75,
0x3d353d35,0xbc95bd75,0xbc483d7b,0x3d22bd46,0xbd6d3cc4,0x3d7f3bc9,0xbd55bd0e,0x3cf13d62,0xbd800000,0x3d623cf1,0xbd0ebd55,0x3bc93d7f,0x3cc4bd6d,0xbd463d22,0x3d7bbc48,0xbd75bc95,
0xbd6dbcc4,0x3cf13d62,0x3c48bd7b,0xbd463d22,0x3d353d35,0xbbc9bd7f,0xbd0e3d55,0x3d75bc95,0xbcc4bd6d,0xbc953d75,0x3d55bd0e,0xbd7fbbc9,0x3d80,0x3d22bd46,0xbd7b3c48,0x3d623cf1,
0xbcc43d6d,0x3d62bcf1,0xbd7bbc48,0x3d223d46,0x3d35bd35,0xbd7f3bc9,0x3d553d0e,0xbc95bd75,0xbd6d3cc4,0x3d753c95,0xbd0ebd55,0xbbc93d7f,0x3d800000,0xbd46bd22,0x3c483d7b,0x3cf1bd62,
0xbd800000,0x3d223d46,0x3c48bd7b,0xbd623cf1,0x3d6d3cc4,0xbc95bd75,0xbd0e3d55,0x3d7fbbc9,0xbd35bd35,0xbbc93d7f,0x3d55bd0e,0xbd75bc95,0x3cc43d6d,0x3cf1bd62,0xbd7b3c48,0x3d463d22,
0x3d80,0x3d46bd22,0xbd7bbc48,0x3cf13d62,0x3cc4bd6d,0xbd753c95,0x3d553d0e,0xbbc9bd7f,0xbd353d35,0x3d7f3bc9,0xbd0ebd55,0xbc953d75,0x3d6dbcc4,0xbd62bcf1,0x3c483d7b,0x3d22bd46,
0xbcc4bd6d,0xbd223d46,0x3d7b3c48,0xbc95bd75,0x3d800000,0xbcf1bd62,0xbd0e3d55,0x3d7f3bc9,0x3d6d3cc4,0xbbc9bd7f,0xbd553d0e,0x3d623cf1,0xbd353d35,0x3d753c95,0xbc48bd7b,0xbd463d22,
0x3d6dbcc4,0xbd46bd22,0xbc483d7b,0x3d75bc95,0x3d80,0x3d62bcf1,0xbd55bd0e,0xbbc93d7f,0xbcc43d6d,0x3d7fbbc9,0xbd0ebd55,0xbcf13d62,0xbd35bd35,0xbc953d75,0x3d7bbc48,0xbd22bd46,
0x3d353d35,0x3cf1bd62,0xbd7bbc48,0x3bc93d7f,0x3d6dbcc4,0xbd22bd46,0xbd0e3d55,0x3d753c95,0xbd800000,0x3c953d75,0x3d55bd0e,0xbd46bd22,0xbcc43d6d,0x3d7f3bc9,0xbc48bd7b,0xbd623cf1,
0x3d35bd35,0xbd62bcf1,0xbc483d7b,0x3d7fbbc9,0xbcc4bd6d,0xbd463d22,0x3d553d0e,0x3c95bd75,0x3d80,0x3d75bc95,0xbd0ebd55,0xbd223d46,0x3d6d3cc4,0x3bc9bd7f,0xbd7b3c48,0x3cf13d62,
0x3cc4bd6d,0xbd75bc95,0xbc483d7b,0x3d7f3bc9,0x3d35bd35,0xbd46bd22,0xbd0e3d55,0x3d623cf1,0x3d6dbcc4,0xbcf1bd62,0xbd553d0e,0x3d223d46,0x3d800000,0xbbc9bd7f,0xbd7b3c48,0x3c953d75,
0x3d6d3cc4,0x3c95bd75,0xbd7bbc48,0xbbc93d7f,0x3d353d35,0x3d22bd46,0xbd55bd0e,0xbcf13d62,0x3cc43d6d,0x3d62bcf1,0xbd0ebd55,0xbd463d22,0x3d80,0x3d7fbbc9,0xbc48bd7b,0xbd753c95,
0xbd800000,0x3d7f3bc9,0xbd7bbc48,0x3d753c95,0xbd6dbcc4,0x3d623cf1,0xbd55bd0e,0x3d463d22,0xbd35bd35,0x3d223d46,0xbd0ebd55,0x3cf13d62,0xbcc4bd6d,0x3c953d75,0xbc48bd7b,0x3bc93d7f,
0x8000bd80,0xbbc93d7f,0x3c48bd7b,0xbc953d75,0x3cc4bd6d,0xbcf13d62,0x3d0ebd55,0xbd223d46,0x3d35bd35,0xbd463d22,0x3d55bd0e,0xbd623cf1,0x3d6dbcc4,0xbd753c95,0x3d7bbc48,0xbd7f3bc9,
0xbcc4bd6d,0x3bc93d7f,0x3c48bd7b,0xbcf13d62,0xbd800000,0x3d753c95,0xbd55bd0e,0x3d223d46,0x3d6d3cc4,0xbd46bd22,0x3d0e3d55,0xbc95bd75,0x3d35bd35,0xbd623cf1,0x3d7bbc48,0xbd7fbbc9,
0xbd6d3cc4,0x3d7fbbc9,0xbd7bbc48,0x3d623cf1,0x80003d80,0x3c95bd75,0xbd0e3d55,0x3d46bd22,0x3cc4bd6d,0xbd223d46,0x3d55bd0e,0xbd753c95,0xbd35bd35,0x3cf13d62,0xbc48bd7b,0xbbc93d7f,
0x3d353d35,0xbc95bd75,0xbc483d7b,0x3d22bd46,0xbd6d3cc4,0x3d7f3bc9,0xbd55bd0e,0x3cf13d62,0xbd800000,0x3d623cf1,0xbd0ebd55,0x3bc93d7f,0x3cc4bd6d,0xbd463d22,0x3d7bbc48,0xbd75bc95,
0xbd353d35,0x3d75bc95,0xbd7bbc48,0x3d463d22,0xbcc4bd6d,0xbbc93d7f,0x3d0ebd55,0xbd623cf1,0x8000bd80,0xbcf13d62,0x3d55bd0e,0xbd7f3bc9,0x3d6d3cc4,0xbd22bd46,0x3c483d7b,0x3c95bd75,
0x3cc4bd6d,0xbd623cf1,0x3d7b3c48,0xbd22bd46,0xbd353d35,0x3d7fbbc9,0xbd55bd0e,0x3c953d75,0x3d6dbcc4,0xbd75bc95,0x3d0e3d55,0x3bc9bd7f,0xbd800000,0x3d463d22,0xbc48bd7b,0xbcf13d62,
0xbd6dbcc4,0x3cf13d62,0x3c48bd7b,0xbd463d22,0x3d353d35,0xbbc9bd7f,0xbd0e3d55,0x3d75bc95,0xbcc4bd6d,0xbc953d75,0x3d55bd0e,0xbd7fbbc9,0x80003d80,0x3d22bd46,0xbd7b3c48,0x3d623cf1,
0x8000bd80,0xbd463d22,0x3d7b3c48,0xbcf1bd62,0xbcc43d6d,0x3d75bc95,0xbd55bd0e,0x3bc93d7f,0x3d35bd35,0xbd7fbbc9,0x3d0e3d55,0x3c95bd75,0xbd6d3cc4,0x3d623cf1,0xbc48bd7b,0xbd223d46,
0xbd800000,0x3d223d46,0x3c48bd7b,0xbd623cf1,0x3d6d3cc4,0xbc95bd75,0xbd0e3d55,0x3d7fbbc9,0xbd35bd35,0xbbc93d7f,0x3d55bd0e,0xbd75bc95,0x3cc43d6d,0x3cf1bd62,0xbd7b3c48,0x3d463d22,
0x3d6dbcc4,0xbd46bd22,0xbc483d7b,0x3d75bc95,0x80003d80,0x3d62bcf1,0xbd55bd0e,0xbbc93d7f,0xbcc43d6d,0x3d7fbbc9,0xbd0ebd55,0xbcf13d62,0xbd35bd35,0xbc953d75,0x3d7bbc48,0xbd22bd46,
0x3cc43d6d,0x3d22bd46,0xbd7bbc48,0x3c953d75,0xbd800000,0x3cf13d62,0x3d0ebd55,0xbd7fbbc9,0xbd6dbcc4,0x3bc93d7f,0x3d55bd0e,0xbd62bcf1,0x3d35bd35,0xbd75bc95,0x3c483d7b,0x3d46bd22,
0xbd353d35,0x3d623cf1,0x3c48bd7b,0xbd7f3bc9,0x3cc43d6d,0x3d46bd22,0xbd55bd0e,0xbc953d75,0x8000bd80,0xbd753c95,0x3d0e3d55,0x3d22bd46,0xbd6dbcc4,0xbbc93d7f,0x3d7bbc48,0xbcf1bd62,
0x3d353d35,0x3cf1bd62,0xbd7bbc48,0x3bc93d7f,0x3d6dbcc4,0xbd22bd46,0xbd0e3d55,0x3d753c95,0xbd800000,0x3c953d75,0x3d55bd0e,0xbd46bd22,0xbcc43d6d,0x3d7f3bc9,0xbc48bd7b,0xbd623cf1,
0x3d6d3cc4,0x3c95bd75,0xbd7bbc48,0xbbc93d7f,0x3d353d35,0x3d22bd46,0xbd55bd0e,0xbcf13d62,0x3cc43d6d,0x3d62bcf1,0xbd0ebd55,0xbd463d22,0x80003d80,0x3d7fbbc9,0xbc48bd7b,0xbd753c95,
0xbcc43d6d,0x3d753c95,0x3c48bd7b,0xbd7fbbc9,0xbd353d35,0x3d463d22,0x3d0ebd55,0xbd62bcf1,0xbd6d3cc4,0x3cf13d62,0x3d55bd0e,0xbd22bd46,0xbd800000,0x3bc93d7f,0x3d7bbc48,0xbc95bd75,
0x3d80,0x3d7f3bc9,0x3c48bd7b,0xbd75bc95,0xbcc43d6d,0x3d623cf1,0x3d0ebd55,0xbd46bd22,0xbd353d35,0x3d223d46,0x3d55bd0e,0xbcf1bd62,0xbd6d3cc4,0x3c953d75,0x3d7bbc48,0xbbc9bd7f,
0xbd800000,0xbbc93d7f,0x3d7b3c48,0x3c95bd75,0xbd6dbcc4,0xbcf13d62,0x3d553d0e,0x3d22bd46,0xbd35bd35,0xbd463d22,0x3d0e3d55,0x3d62bcf1,0xbcc4bd6d,0xbd753c95,0x3c483d7b,0x3d7fbbc9,
0xbd6d3cc4,0x3bc93d7f,0x3d7b3c48,0x3cf1bd62,0x3d80,0x3d753c95,0x3d0ebd55,0xbd22bd46,0x3cc4bd6d,0xbd46bd22,0xbd553d0e,0x3c953d75,0xbd35bd35,0xbd623cf1,0x3c483d7b,0x3d7f3bc9,
0x3cc43d6d,0x3d7fbbc9,0x3c48bd7b,0xbd62bcf1,0x3d800000,0x3c95bd75,0xbd55bd0e,0xbd463d22,0xbd6dbcc4,0xbd223d46,0x3d0e3d55,0x3d75bc95,0xbd353d35,0x3cf13d62,0x3d7bbc48,0x3bc9bd7f,
0x3d35bd35,0xbc95bd75,0xbd7bbc48,0xbd223d46,0x3cc43d6d,0x3d7f3bc9,0x3d0ebd55,0xbcf1bd62,0x3d80,0x3d623cf1,0x3d55bd0e,0xbbc9bd7f,0xbd6dbcc4,0xbd463d22,0x3c483d7b,0x3d753c95,
0x3d353d35,0x3d75bc95,0x3c48bd7b,0xbd46bd22,0xbd6d3cc4,0xbbc93d7f,0x3d553d0e,0x3d62bcf1,0xbd800000,0xbcf13d62,0x3d0e3d55,0x3d7fbbc9,0x3cc4bd6d,0xbd22bd46,0xbd7b3c48,0xbc953d75,
0xbd6dbcc4,0xbd623cf1,0xbc483d7b,0x3d223d46,0x3d353d35,0x3d7fbbc9,0x3d0ebd55,0xbc95bd75,0xbcc4bd6d,0xbd75bc95,0xbd553d0e,0xbbc93d7f,0x3d80,0x3d463d22,0x3d7bbc48,0x3cf1bd62,
0xbcc43d6d,0x3cf13d62,0x3d7b3c48,0x3d46bd22,0x3d35bd35,0xbbc9bd7f,0xbd55bd0e,0xbd753c95,0xbd6d3cc4,0xbc953d75,0x3d0e3d55,0x3d7f3bc9,0x3d800000,0x3d22bd46,0xbc48bd7b,0xbd62bcf1,
0xbd800000,0xbd463d22,0xbc483d7b,0x3cf13d62,0x3d6d3cc4,0x3d75bc95,0x3d0ebd55,0xbbc9bd7f,0xbd35bd35,0xbd7fbbc9,0xbd553d0e,0xbc953d75,0x3cc43d6d,0x3d623cf1,0x3d7bbc48,0x3d22bd46,
0x3d80,0x3d223d46,0x3d7b3c48,0x3d62bcf1,0x3cc4bd6d,0xbc95bd75,0xbd55bd0e,0xbd7f3bc9,0xbd353d35,0xbbc93d7f,0x3d0e3d55,0x3d753c95,0x3d6dbcc4,0x3cf1bd62,0xbc48bd7b,0xbd46bd22,
0xbcc4bd6d,0xbd46bd22,0xbd7bbc48,0xbd753c95,0x3d800000,0x3d62bcf1,0x3d0ebd55,0x3bc9bd7f,0x3d6d3cc4,0x3d7fbbc9,0x3d55bd0e,0x3cf1bd62,0xbd353d35,0xbc953d75,0x3c483d7b,0x3d223d46,
0x3d6dbcc4,0x3d22bd46,0x3c48bd7b,0xbc95bd75,0x3d80,0x3cf13d62,0x3d553d0e,0x3d7f3bc9,0xbcc43d6d,0x3bc93d7f,0x3d0e3d55,0x3d623cf1,0xbd35bd35,0xbd75bc95,0xbd7b3c48,0xbd463d22,
0x3d353d35,0x3d623cf1,0x3d7b3c48,0x3d7fbbc9,0x3d6dbcc4,0x3d46bd22,0x3d0ebd55,0x3c95bd75,0xbd800000,0xbd753c95,0xbd553d0e,0xbd223d46,0xbcc43d6d,0xbbc93d7f,0x3c483d7b,0x3cf13d62,
0x3d35bd35,0x3cf1bd62,0x3c48bd7b,0xbbc9bd7f,0xbcc4bd6d,0xbd22bd46,0xbd55bd0e,0xbd75bc95,0x3d80,0x3c953d75,0x3d0e3d55,0x3d463d22,0x3d6d3cc4,0x3d7f3bc9,0x3d7bbc48,0x3d62bcf1,
0x3cc4bd6d,0x3c95bd75,0x3c48bd7b,0x3bc9bd7f,0x3d35bd35,0x3d22bd46,0x3d0ebd55,0x3cf1bd62,0x3d6dbcc4,0x3d62bcf1,0x3d55bd0e,0x3d46bd22,0x3d800000,0x3d7fbbc9,0x3d7bbc48,0x3d75bc95,
0x3d6d3cc4,0x3d753c95,0x3d7b3c48,0x3d7f3bc9,0x3d353d35,0x3d463d22,0x3d553d0e,0x3d623cf1,0x3cc43d6d,0x3cf13d62,0x3d0e3d55,0x3d223d46,0x3d80,0x3bc93d7f,0x3c483d7b,0x3c953d75,
0xbd800000,0xbbc93d7f,0x3d7b3c48,0x3c95bd75,0xbd6dbcc4,0xbcf13d62,0x3d553d0e,0x3d22bd46,0xbd35bd35,0xbd463d22,0x3d0e3d55,0x3d62bcf1,0xbcc4bd6d,0xbd753c95,0x3c483d7b,0x3d7fbbc9,
0x8000bd80,0xbd7fbbc9,0xbc483d7b,0x3d753c95,0x3cc4bd6d,0xbd62bcf1,0xbd0e3d55,0x3d463d22,0x3d35bd35,0xbd22bd46,0xbd553d0e,0x3cf13d62,0x3d6dbcc4,0xbc95bd75,0xbd7b3c48,0x3bc93d7f,
0xbcc4bd6d,0xbd7f3bc9,0xbc483d7b,0x3d623cf1,0xbd800000,0xbc953d75,0x3d553d0e,0x3d46bd22,0x3d6d3cc4,0x3d22bd46,0xbd0ebd55,0xbd753c95,0x3d35bd35,0xbcf1bd62,0xbd7b3c48,0xbbc93d7f,
0xbd6d3cc4,0x3bc93d7f,0x3d7b3c48,0x3cf1bd62,0x80003d80,0x3d753c95,0x3d0ebd55,0xbd22bd46,0x3cc4bd6d,0xbd46bd22,0xbd553d0e,0x3c953d75,0xbd35bd35,0xbd623cf1,0x3c483d7b,0x3d7f3bc9,
0x3d353d35,0x3d75bc95,0x3c48bd7b,0xbd46bd22,0xbd6d3cc4,0xbbc93d7f,0x3d553d0e,0x3d62bcf1,0xbd800000,0xbcf13d62,0x3d0e3d55,0x3d7fbbc9,0x3cc4bd6d,0xbd22bd46,0xbd7b3c48,0xbc953d75,
0xbd353d35,0x3c953d75,0x3d7b3c48,0x3d22bd46,0xbcc4bd6d,0xbd7fbbc9,0xbd0e3d55,0x3cf13d62,0x8000bd80,0xbd62bcf1,0xbd553d0e,0x3bc93d7f,0x3d6d3cc4,0x3d46bd22,0xbc48bd7b,0xbd75bc95,
0x3cc4bd6d,0xbcf1bd62,0xbd7bbc48,0xbd463d22,0xbd353d35,0x3bc93d7f,0x3d553d0e,0x3d75bc95,0x3d6dbcc4,0x3c95bd75,0xbd0ebd55,0xbd7fbbc9,0xbd800000,0xbd223d46,0x3c483d7b,0x3d623cf1,
0xbd6dbcc4,0xbd623cf1,0xbc483d7b,0x3d223d46,0x3d353d35,0x3d7fbbc9,0x3d0ebd55,0xbc95bd75,0xbcc4bd6d,0xbd75bc95,0xbd553d0e,0xbbc93d7f,0x80003d80,0x3d463d22,0x3d7bbc48,0x3cf1bd62,
0x8000bd80,0xbd22bd46,0xbd7bbc48,0xbd623cf1,0xbcc43d6d,0x3c953d75,0x3d553d0e,0x3d7fbbc9,0x3d35bd35,0x3bc9bd7f,0xbd0ebd55,0xbd75bc95,0xbd6d3cc4,0xbcf13d62,0x3c483d7b,0x3d463d22,
0xbd800000,0xbd463d22,0xbc483d7b,0x3cf13d62,0x3d6d3cc4,0x3d75bc95,0x3d0ebd55,0xbbc9bd7f,0xbd35bd35,0xbd7fbbc9,0xbd553d0e,0xbc953d75,0x3cc43d6d,0x3d623cf1,0x3d7bbc48,0x3d22bd46,
0x3d6dbcc4,0x3d22bd46,0x3c48bd7b,0xbc95bd75,0x80003d80,0x3cf13d62,0x3d553d0e,0x3d7f3bc9,0xbcc43d6d,0x3bc93d7f,0x3d0e3d55,0x3d623cf1,0xbd35bd35,0xbd75bc95,0xbd7b3c48,0xbd463d22,
0x3cc43d6d,0x3d463d22,0x3d7b3c48,0x3d75bc95,0xbd800000,0xbd623cf1,0xbd0e3d55,0xbbc93d7f,0xbd6dbcc4,0xbd7f3bc9,0xbd553d0e,0xbcf13d62,0x3d35bd35,0x3c95bd75,0xbc48bd7b,0xbd22bd46,
0xbd353d35,0xbcf13d62,0xbc483d7b,0x3bc93d7f,0x3cc43d6d,0x3d223d46,0x3d553d0e,0x3d753c95,0x8000bd80,0xbc95bd75,0xbd0ebd55,0xbd46bd22,0xbd6dbcc4,0xbd7fbbc9,0xbd7b3c48,0xbd623cf1,
0x3d353d35,0x3d623cf1,0x3d7b3c48,0x3d7fbbc9,0x3d6dbcc4,0x3d46bd22,0x3d0ebd55,0x3c95bd75,0xbd800000,0xbd753c95,0xbd553d0e,0xbd223d46,0xbcc43d6d,0xbbc93d7f,0x3c483d7b,0x3cf13d62,
0x3d6d3cc4,0x3d753c95,0x3d7b3c48,0x3d7f3bc9,0x3d353d35,0x3d463d22,0x3d553d0e,0x3d623cf1,0x3cc43d6d,0x3cf13d62,0x3d0e3d55,0x3d223d46,0x80003d80,0x3bc93d7f,0x3c483d7b,0x3c953d75,
0xbcc43d6d,0xbc953d75,0xbc483d7b,0xbbc93d7f,0xbd353d35,0xbd223d46,0xbd0e3d55,0xbcf13d62,0xbd6d3cc4,0xbd623cf1,0xbd553d0e,0xbd463d22,0xbd800000,0xbd7f3bc9,0xbd7b3c48,0xbd753c95,
0x3d80,0xbc163d7d,0xbc953d75,0xbcdb3d67,0xbd0e3d55,0xbd2c3d3e,0xbd463d22,0xbd5c3d04,0xbd6d3cc4,0xbd783c79,0xbd7f3bc9,0xbd80bb49,0xbd7bbc48,0xbd71bcac,0xbd62bcf1,0xbd4ebd18,
0xbd35bd35,0xbd18bd4e,0xbcf1bd62,0xbcacbd71,0xbc48bd7b,0xbb49bd80,0x3bc9bd7f,0x3c79bd78,0x3cc4bd6d,0x3d04bd5c,0x3d22bd46,0x3d3ebd2c,0x3d55bd0e,0x3d67bcdb,0x3d75bc95,0x3d7dbc16,
0xbd7b3c48,0xbd7dbc16,0xbd62bcf1,0xbd2cbd3e,0x3d80,0xbcac3d71,0xbd223d46,0xbd5c3d04,0x3d55bd0e,0x3d78bc79,0x3d7f3bc9,0x3d673cdb,0xbcc4bd6d,0xbb49bd80,0x3c95bd75,0x3d18bd4e,
0xbd0e3d55,0xbd4e3d18,0xbd753c95,0xbd80bb49,0x3d353d35,0x3cdb3d67,0x3bc93d7f,0xbc793d78,0x3c48bd7b,0x3d04bd5c,0x3d46bd22,0x3d71bcac,0xbd6dbcc4,0xbd3ebd2c,0xbcf1bd62,0xbc16bd7d,
0x3d6dbcc4,0x3d7d3c16,0x3d463d22,0x3cac3d71,0xbc483d7b,0xbd2c3d3e,0xbd753c95,0xbd78bc79,0x3d80,0xbd043d5c,0xbd623cf1,0xbd80bb49,0xbd55bd0e,0xbcdbbd67,0x3bc9bd7f,0x3d18bd4e,
0xbcc43d6d,0xbd4e3d18,0xbd7f3bc9,0xbd67bcdb,0xbd0ebd55,0xbb49bd80,0x3cf1bd62,0x3d5cbd04,0xbd35bd35,0xbc79bd78,0x3c95bd75,0x3d3ebd2c,0x3d7bbc48,0x3d713cac,0x3d223d46,0x3c163d7d,
0xbd0ebd55,0x3c16bd7d,0x3d46bd22,0x3d803b49,0x3cc43d6d,0xbcac3d71,0xbd623cf1,0xbd78bc79,0xbc48bd7b,0x3d04bd5c,0x3d75bc95,0x3d673cdb,0x3d80,0xbd2c3d3e,0xbd7f3bc9,0xbd4ebd18,
0xbd7bbc48,0xbd18bd4e,0x3bc9bd7f,0x3d3ebd2c,0x3d6d3cc4,0x3cdb3d67,0xbc953d75,0xbd5c3d04,0xbd55bd0e,0xbc79bd78,0x3cf1bd62,0x3d71bcac,0x3d353d35,0x3b493d80,0xbd223d46,0xbd7d3c16,
0xbd35bd35,0x3c16bd7d,0x3d62bcf1,0x3d673cdb,0x3c483d7b,0xbd2c3d3e,0xbd7fbbc9,0xbd04bd5c,0x3cc4bd6d,0x3d78bc79,0x3d463d22,0xbb493d80,0xbd553d0e,0xbd71bcac,0xbc95bd75,0x3d18bd4e,
0x3d80,0xbd4e3d18,0xbd75bc95,0xbcacbd71,0x3d0ebd55,0x3d80bb49,0x3d223d46,0xbc793d78,0xbd6d3cc4,0xbd5cbd04,0xbbc9bd7f,0x3d3ebd2c,0x3d7b3c48,0x3cdb3d67,0xbcf13d62,0xbd7d3c16,
0x3d0ebd55,0x3d7d3c16,0x3c953d75,0xbd3e3d2c,0x3d353d35,0xbcac3d71,0xbd7f3bc9,0xbd04bd5c,0xbc483d7b,0xbd783c79,0xbd22bd46,0x3cdbbd67,0xbd6dbcc4,0xbb49bd80,0x3d62bcf1,0x3d4e3d18,
0x3d7bbc48,0x3d183d4e,0xbcf13d62,0xbd80bb49,0x3d80,0xbd673cdb,0xbd46bd22,0x3c79bd78,0xbd553d0e,0xbd5cbd04,0x3bc9bd7f,0x3d71bcac,0xbcc4bd6d,0x3d2cbd3e,0x3d753c95,0x3c163d7d,
0xbcc43d6d,0xbd7dbc16,0xbbc9bd7f,0x3d71bcac,0x3d0e3d55,0xbd2c3d3e,0xbd62bcf1,0x3c79bd78,0xbd35bd35,0x3d04bd5c,0x3d753c95,0xbb493d80,0xbd7b3c48,0xbcdbbd67,0x3d46bd22,0x3d4e3d18,
0x3d6dbcc4,0x3d183d4e,0xbd223d46,0xbd67bcdb,0x3c48bd7b,0x3d80bb49,0x3c953d75,0xbd5c3d04,0x3d80,0xbd783c79,0xbcf1bd62,0x3d3ebd2c,0x3d553d0e,0xbcac3d71,0xbd7fbbc9,0xbc16bd7d,
0x3d7b3c48,0xbc163d7d,0xbd7fbbc9,0x3b49bd80,0x3d6d3cc4,0xbcac3d71,0xbd75bc95,0x3c79bd78,0x3d553d0e,0xbd043d5c,0xbd62bcf1,0x3cdbbd67,0x3d353d35,0xbd2c3d3e,0xbd46bd22,0x3d18bd4e,
0x3d0e3d55,0xbd4e3d18,0xbd22bd46,0x3d3ebd2c,0x3cc43d6d,0xbd673cdb,0xbcf1bd62,0x3d5cbd04,0x3c483d7b,0xbd783c79,0xbc95bd75,0x3d71bcac,0x3d80,0xbd803b49,0xbbc9bd7f,0x3d7dbc16,
0xbd800000,0xbd7dbc16,0xbd75bc95,0xbd67bcdb,0xbd55bd0e,0xbd3ebd2c,0xbd22bd46,0xbd04bd5c,0xbcc4bd6d,0xbc79bd78,0xbbc9bd7f,0x3b49bd80,0x3c48bd7b,0x3cacbd71,0x3cf1bd62,0x3d18bd4e,
0x3d35bd35,0x3d4ebd18,0x3d62bcf1,0x3d71bcac,0x3d7bbc48,0x3d80bb49,0x3d7f3bc9,0x3d783c79,0x3d6d3cc4,0x3d5c3d04,0x3d463d22,0x3d2c3d3e,0x3d0e3d55,0x3cdb3d67,0x3c953d75,0x3c163d7d,
0xbc48bd7b,0x3c16bd7d,0x3cf1bd62,0x3d3ebd2c,0xbd800000,0xbd71bcac,0xbd46bd22,0xbd04bd5c,0x3d0e3d55,0x3c793d78,0xbbc93d7f,0xbcdb3d67,0x3d6dbcc4,0x3d80bb49,0x3d753c95,0x3d4e3d18,
0xbd55bd0e,0xbd18bd4e,0xbc95bd75,0x3b49bd80,0xbd353d35,0xbd673cdb,0xbd7f3bc9,0xbd78bc79,0x3d7b3c48,0x3d5c3d04,0x3d223d46,0x3cac3d71,0x3cc4bd6d,0x3d2cbd3e,0x3d62bcf1,0x3d7dbc16,
0x3cc43d6d,0xbc163d7d,0xbd223d46,0xbd713cac,0xbd7bbc48,0xbd3ebd2c,0xbc95bd75,0x3c79bd78,0xbd800000,0xbd5cbd04,0xbcf1bd62,0x3b49bd80,0x3d0ebd55,0x3d67bcdb,0x3d7f3bc9,0x3d4e3d18,
0xbd6dbcc4,0xbd18bd4e,0xbbc9bd7f,0x3cdbbd67,0x3d55bd0e,0x3d80bb49,0x3d623cf1,0x3d043d5c,0x3d35bd35,0x3d78bc79,0x3d753c95,0x3d2c3d3e,0x3c483d7b,0xbcac3d71,0xbd463d22,0xbd7d3c16,
0x3d55bd0e,0x3d7d3c16,0x3d223d46,0xbb493d80,0xbd6d3cc4,0xbd71bcac,0xbcf1bd62,0x3c79bd78,0x3d7bbc48,0x3d5c3d04,0x3c953d75,0xbcdb3d67,0xbd800000,0xbd3ebd2c,0xbbc9bd7f,0x3d18bd4e,
0x3c48bd7b,0x3d4ebd18,0x3d7f3bc9,0x3d2c3d3e,0xbcc43d6d,0xbd673cdb,0xbd75bc95,0xbd04bd5c,0x3d0ebd55,0x3d78bc79,0x3d623cf1,0x3cac3d71,0xbd353d35,0xbd803b49,0xbd46bd22,0xbc16bd7d,
0x3d35bd35,0x3d7d3c16,0x3cf13d62,0xbcdb3d67,0xbd7b3c48,0xbd3ebd2c,0x3bc9bd7f,0x3d5cbd04,0x3d6d3cc4,0x3c793d78,0xbd223d46,0xbd80bb49,0xbd0ebd55,0x3cacbd71,0x3d75bc95,0x3d4e3d18,
0xbd800000,0xbd18bd4e,0x3c95bd75,0x3d71bcac,0x3d553d0e,0x3b493d80,0xbd463d22,0xbd78bc79,0xbcc4bd6d,0x3d04bd5c,0x3d7fbbc9,0x3d2c3d3e,0xbc483d7b,0xbd673cdb,0xbd62bcf1,0xbc16bd7d,
0x3d553d0e,0xbc163d7d,0xbd753c95,0xbd2cbd3e,0xbd353d35,0xbd71bcac,0xbbc9bd7f,0x3d5cbd04,0xbd7bbc48,0xbc79bd78,0x3d46bd22,0x3d673cdb,0x3cc4bd6d,0x3d80bb49,0x3cf13d62,0xbd183d4e,
0x3c483d7b,0xbd4e3d18,0xbd62bcf1,0x3b49bd80,0xbd800000,0xbcdbbd67,0x3d22bd46,0x3d783c79,0xbd0ebd55,0x3d04bd5c,0x3d7f3bc9,0x3cac3d71,0x3d6dbcc4,0x3d3e3d2c,0xbc953d75,0xbd7d3c16,
0xbd6dbcc4,0x3c16bd7d,0x3d7fbbc9,0x3cac3d71,0xbd553d0e,0xbd3ebd2c,0x3cf1bd62,0x3d783c79,0x3d35bd35,0x3d5c3d04,0xbc953d75,0xbd80bb49,0xbc48bd7b,0x3d67bcdb,0x3d223d46,0xbd183d4e,
0x3cc43d6d,0xbd4e3d18,0xbd46bd22,0x3cdbbd67,0x3d7b3c48,0x3b493d80,0xbd753c95,0xbd04bd5c,0xbd800000,0xbc79bd78,0x3d62bcf1,0x3d2c3d3e,0xbd0e3d55,0xbd71bcac,0x3bc9bd7f,0x3d7dbc16,
0xbc483d7b,0xbd7dbc16,0x3bc9bd7f,0x3d803b49,0xbcc43d6d,0xbd71bcac,0x3c95bd75,0x3d783c79,0xbd0e3d55,0xbd5cbd04,0x3cf1bd62,0x3d673cdb,0xbd353d35,0xbd3ebd2c,0x3d22bd46,0x3d4e3d18,
0xbd553d0e,0xbd18bd4e,0x3d46bd22,0x3d2c3d3e,0xbd6d3cc4,0xbcdbbd67,0x3d62bcf1,0x3d043d5c,0xbd7b3c48,0xbc79bd78,0x3d75bc95,0x3cac3d71,0xbd800000,0xbb49bd80,0x3d7fbbc9,0x3c163d7d,
0x3d80,0xbd7dbc16,0x3c95bd75,0x3d673cdb,0xbd0e3d55,0xbd3ebd2c,0x3d46bd22,0x3d043d5c,0xbd6d3cc4,0xbc79bd78,0x3d7fbbc9,0xbb493d80,0xbd7bbc48,0x3cacbd71,0x3d623cf1,0xbd183d4e,
0xbd35bd35,0x3d4ebd18,0x3cf13d62,0xbd713cac,0xbc48bd7b,0x3d80bb49,0xbbc93d7f,0xbd78bc79,0x3cc4bd6d,0x3d5c3d04,0xbd223d46,0xbd2cbd3e,0x3d55bd0e,0x3cdb3d67,0xbd753c95,0xbc16bd7d,
0xbd7b3c48,0x3c16bd7d,0x3d623cf1,0xbd3e3d2c,0x3d80,0xbd71bcac,0x3d22bd46,0x3d043d5c,0x3d55bd0e,0x3c793d78,0xbd7fbbc9,0x3cdbbd67,0xbcc4bd6d,0x3d80bb49,0xbc953d75,0xbd4ebd18,
0xbd0e3d55,0xbd18bd4e,0x3d75bc95,0xbb493d80,0x3d353d35,0xbd673cdb,0xbbc9bd7f,0x3d783c79,0x3c48bd7b,0x3d5c3d04,0xbd463d22,0xbcacbd71,0xbd6dbcc4,0x3d2cbd3e,0x3cf13d62,0xbd7d3c16,
0x3d6dbcc4,0xbc163d7d,0xbd46bd22,0x3d71bcac,0xbc483d7b,0xbd3ebd2c,0x3d75bc95,0xbc793d78,0x3d80,0xbd5cbd04,0x3d62bcf1,0xbb493d80,0xbd55bd0e,0x3d67bcdb,0xbbc93d7f,0xbd4ebd18,
0xbcc43d6d,0xbd18bd4e,0x3d7fbbc9,0xbcdb3d67,0xbd0ebd55,0x3d80bb49,0xbcf13d62,0xbd04bd5c,0xbd35bd35,0x3d78bc79,0xbc953d75,0xbd2cbd3e,0x3d7bbc48,0xbcac3d71,0xbd22bd46,0x3d7dbc16,
0xbd0ebd55,0x3d7d3c16,0xbd463d22,0x3b49bd80,0x3cc43d6d,0xbd71bcac,0x3d62bcf1,0xbc793d78,0xbc48bd7b,0x3d5c3d04,0xbd753c95,0x3cdbbd67,0x3d80,0xbd3ebd2c,0x3d7fbbc9,0xbd183d4e,
0xbd7bbc48,0x3d4ebd18,0xbbc93d7f,0xbd2cbd3e,0x3d6d3cc4,0xbd673cdb,0x3c95bd75,0x3d043d5c,0xbd55bd0e,0x3d78bc79,0xbcf13d62,0xbcacbd71,0x3d353d35,0xbd803b49,0x3d22bd46,0x3c163d7d,
0xbd35bd35,0x3d7d3c16,0xbd623cf1,0x3cdbbd67,0x3c483d7b,0xbd3ebd2c,0x3d7f3bc9,0xbd5c3d04,0x3cc4bd6d,0x3c793d78,0xbd46bd22,0x3d803b49,0xbd553d0e,0x3cacbd71,0x3c953d75,0xbd4ebd18,
0x3d80,0xbd18bd4e,0x3d753c95,0xbd713cac,0x3d0ebd55,0x3b493d80,0xbd22bd46,0x3d783c79,0xbd6d3cc4,0x3d04bd5c,0x3bc93d7f,0xbd2cbd3e,0x3d7b3c48,0xbd673cdb,0x3cf1bd62,0x3c163d7d,
0x3d0ebd55,0xbc163d7d,0xbc95bd75,0x3d2c3d3e,0x3d353d35,0xbd71bcac,0x3d7fbbc9,0xbd5c3d04,0xbc483d7b,0xbc79bd78,0x3d223d46,0xbd67bcdb,0xbd6dbcc4,0x3d80bb49,0xbd623cf1,0x3d18bd4e,
0x3d7bbc48,0xbd4e3d18,0x3cf1bd62,0xbb493d80,0x3d80,0xbcdbbd67,0x3d463d22,0xbd78bc79,0xbd553d0e,0x3d04bd5c,0xbbc93d7f,0xbcacbd71,0xbcc4bd6d,0x3d3e3d2c,0xbd75bc95,0x3d7dbc16,
0xbcc43d6d,0x3c16bd7d,0x3bc93d7f,0xbcacbd71,0x3d0e3d55,0xbd3ebd2c,0x3d623cf1,0xbd78bc79,0xbd35bd35,0x3d5c3d04,0xbd75bc95,0x3d803b49,0xbd7b3c48,0x3d67bcdb,0xbd463d22,0x3d18bd4e,
0x3d6dbcc4,0xbd4e3d18,0x3d22bd46,0xbcdb3d67,0x3c48bd7b,0x3b493d80,0xbc95bd75,0x3d043d5c,0x3d80,0xbc79bd78,0x3cf13d62,0xbd2cbd3e,0x3d553d0e,0xbd71bcac,0x3d7f3bc9,0xbd7d3c16,
0x3d7b3c48,0xbd7dbc16,0x3d7f3bc9,0xbd80bb49,0x3d6d3cc4,0xbd71bcac,0x3d753c95,0xbd78bc79,0x3d553d0e,0xbd5cbd04,0x3d623cf1,0xbd67bcdb,0x3d353d35,0xbd3ebd2c,0x3d463d22,0xbd4ebd18,
0x3d0e3d55,0xbd18bd4e,0x3d223d46,0xbd2cbd3e,0x3cc43d6d,0xbcdbbd67,0x3cf13d62,0xbd04bd5c,0x3c483d7b,0xbc79bd78,0x3c953d75,0xbcacbd71,0x3d80,0xbb49bd80,0x3bc93d7f,0xbc16bd7d,
0xbd800000,0x3c16bd7d,0x3d753c95,0xbcdb3d67,0xbd55bd0e,0x3d2cbd3e,0x3d223d46,0xbd5c3d04,0xbcc4bd6d,0x3d78bc79,0x3bc93d7f,0xbd80bb49,0x3c48bd7b,0x3d713cac,0xbcf13d62,0xbd4ebd18,
0x3d35bd35,0x3d183d4e,0xbd623cf1,0xbcacbd71,0x3d7bbc48,0x3b493d80,0xbd7fbbc9,0x3c79bd78,0x3d6d3cc4,0xbd043d5c,0xbd46bd22,0x3d3ebd2c,0x3d0e3d55,0xbd673cdb,0xbc95bd75,0x3d7dbc16,
0xbc48bd7b,0x3d7d3c16,0xbcf13d62,0xbd2cbd3e,0xbd800000,0x3cacbd71,0x3d463d22,0xbd5c3d04,0x3d0e3d55,0xbd783c79,0x3bc9bd7f,0x3d673cdb,0x3d6dbcc4,0x3b493d80,0xbd75bc95,0x3d18bd4e,
0xbd55bd0e,0x3d4ebd18,0x3c953d75,0xbd80bb49,0xbd353d35,0xbcdbbd67,0x3d7fbbc9,0xbc793d78,0x3d7b3c48,0xbd043d5c,0xbd22bd46,0x3d71bcac,0x3cc4bd6d,0x3d3e3d2c,0xbd623cf1,0xbc16bd7d,
0x3cc43d6d,0xbd7dbc16,0x3d22bd46,0x3cac3d71,0xbd7bbc48,0x3d2cbd3e,0x3c953d75,0xbd78bc79,0xbd800000,0x3d04bd5c,0x3cf13d62,0xbd80bb49,0x3d0ebd55,0x3cdb3d67,0xbd7fbbc9,0x3d18bd4e,
0xbd6dbcc4,0x3d4ebd18,0x3bc93d7f,0xbd67bcdb,0x3d55bd0e,0x3b493d80,0xbd62bcf1,0x3d5cbd04,0x3d35bd35,0x3c793d78,0xbd75bc95,0x3d3ebd2c,0x3c483d7b,0xbd71bcac,0x3d46bd22,0x3c163d7d,
0x3d55bd0e,0xbc163d7d,0xbd22bd46,0x3d803b49,0xbd6d3cc4,0x3cacbd71,0x3cf13d62,0xbd78bc79,0x3d7bbc48,0xbd043d5c,0xbc95bd75,0x3d673cdb,0xbd800000,0x3d2cbd3e,0x3bc93d7f,0xbd4ebd18,
0x3c48bd7b,0x3d183d4e,0xbd7fbbc9,0x3d3ebd2c,0xbcc43d6d,0xbcdbbd67,0x3d753c95,0xbd5c3d04,0x3d0ebd55,0x3c793d78,0xbd62bcf1,0x3d71bcac,0xbd353d35,0xbb49bd80,0x3d463d22,0xbd7d3c16,
0x3d35bd35,0xbc163d7d,0xbcf1bd62,0x3d673cdb,0xbd7b3c48,0x3d2cbd3e,0xbbc93d7f,0xbd04bd5c,0x3d6d3cc4,0xbd783c79,0x3d22bd46,0xbb493d80,0xbd0ebd55,0x3d713cac,0xbd753c95,0x3d18bd4e,
0xbd800000,0x3d4ebd18,0xbc953d75,0xbcacbd71,0x3d553d0e,0xbd803b49,0x3d46bd22,0xbc793d78,0xbcc4bd6d,0x3d5c3d04,0xbd7f3bc9,0x3d3ebd2c,0xbc483d7b,0xbcdbbd67,0x3d623cf1,0xbd7d3c16,
0x3d553d0e,0xbd7dbc16,0x3d75bc95,0xbd3e3d2c,0xbd353d35,0x3cacbd71,0x3bc93d7f,0xbd04bd5c,0xbd7bbc48,0x3d78bc79,0xbd463d22,0x3cdbbd67,0x3cc4bd6d,0x3b493d80,0xbcf1bd62,0x3d4e3d18,
0x3c483d7b,0xbd18bd4e,0x3d623cf1,0xbd80bb49,0xbd800000,0x3d67bcdb,0xbd223d46,0x3c79bd78,0xbd0ebd55,0x3d5c3d04,0xbd7fbbc9,0x3d71bcac,0x3d6dbcc4,0xbd2c3d3e,0x3c95bd75,0x3c163d7d,
0xbd6dbcc4,0x3d7d3c16,0xbd7f3bc9,0x3d71bcac,0xbd553d0e,0x3d2cbd3e,0xbcf13d62,0x3c79bd78,0x3d35bd35,0xbd043d5c,0x3c95bd75,0xbb493d80,0xbc48bd7b,0x3cdb3d67,0xbd22bd46,0x3d4e3d18,
0x3cc43d6d,0xbd18bd4e,0x3d463d22,0xbd67bcdb,0x3d7b3c48,0xbd803b49,0x3d75bc95,0xbd5c3d04,0xbd800000,0x3d78bc79,0xbd623cf1,0x3d3ebd2c,0xbd0e3d55,0x3cacbd71,0xbbc93d7f,0xbc16bd7d,
0xbc483d7b,0x3c16bd7d,0xbbc93d7f,0x3b49bd80,0xbcc43d6d,0x3cacbd71,0xbc953d75,0x3c79bd78,0xbd0e3d55,0x3d04bd5c,0xbcf13d62,0x3cdbbd67,0xbd353d35,0x3d2cbd3e,0xbd223d46,0x3d18bd4e,
0xbd553d0e,0x3d4ebd18,0xbd463d22,0x3d3ebd2c,0xbd6d3cc4,0x3d67bcdb,0xbd623cf1,0x3d5cbd04,0xbd7b3c48,0x3d78bc79,0xbd753c95,0x3d71bcac,0xbd800000,0x3d80bb49,0xbd7f3bc9,0x3d7dbc16,
0x3d80,0x3c16bd7d,0xbc953d75,0x3cdbbd67,0xbd0e3d55,0x3d2cbd3e,0xbd463d22,0x3d5cbd04,0xbd6d3cc4,0x3d78bc79,0xbd7f3bc9,0x3d803b49,0xbd7bbc48,0x3d713cac,0xbd62bcf1,0x3d4e3d18,
0xbd35bd35,0x3d183d4e,0xbcf1bd62,0x3cac3d71,0xbc48bd7b,0x3b493d80,0x3bc9bd7f,0xbc793d78,0x3cc4bd6d,0xbd043d5c,0x3d22bd46,0xbd3e3d2c,0x3d55bd0e,0xbd673cdb,0x3d75bc95,0xbd7d3c16,
0xbd7b3c48,0x3d7d3c16,0xbd62bcf1,0x3d2c3d3e,0x3d80,0x3cacbd71,0xbd223d46,0x3d5cbd04,0x3d55bd0e,0xbd783c79,0x3d7f3bc9,0xbd67bcdb,0xbcc4bd6d,0x3b493d80,0x3c95bd75,0xbd183d4e,
0xbd0e3d55,0x3d4ebd18,0xbd753c95,0x3d803b49,0x3d353d35,0xbcdbbd67,0x3bc93d7f,0x3c79bd78,0x3c48bd7b,0xbd043d5c,0x3d46bd22,0xbd713cac,0xbd6dbcc4,0x3d3e3d2c,0xbcf1bd62,0x3c163d7d,
0x3d6dbcc4,0xbd7dbc16,0x3d463d22,0xbcacbd71,0xbc483d7b,0x3d2cbd3e,0xbd753c95,0x3d783c79,0x3d80,0x3d04bd5c,0xbd623cf1,0x3d803b49,0xbd55bd0e,0x3cdb3d67,0x3bc9bd7f,0xbd183d4e,
0xbcc43d6d,0x3d4ebd18,0xbd7f3bc9,0x3d673cdb,0xbd0ebd55,0x3b493d80,0x3cf1bd62,0xbd5c3d04,0xbd35bd35,0x3c793d78,0x3c95bd75,0xbd3e3d2c,0x3d7bbc48,0xbd71bcac,0x3d223d46,0xbc16bd7d,
0xbd0ebd55,0xbc163d7d,0x3d46bd22,0xbd80bb49,0x3cc43d6d,0x3cacbd71,0xbd623cf1,0x3d783c79,0xbc48bd7b,0xbd043d5c,0x3d75bc95,0xbd67bcdb,0x3d80,0x3d2cbd3e,0xbd7f3bc9,0x3d4e3d18,
0xbd7bbc48,0x3d183d4e,0x3bc9bd7f,0xbd3e3d2c,0x3d6d3cc4,0xbcdbbd67,0xbc953d75,0x3d5cbd04,0xbd55bd0e,0x3c793d78,0x3cf1bd62,0xbd713cac,0x3d353d35,0xbb49bd80,0xbd223d46,0x3d7dbc16,
0xbd35bd35,0xbc163d7d,0x3d62bcf1,0xbd67bcdb,0x3c483d7b,0x3d2cbd3e,0xbd7fbbc9,0x3d043d5c,0x3cc4bd6d,0xbd783c79,0x3d463d22,0x3b49bd80,0xbd553d0e,0x3d713cac,0xbc95bd75,0xbd183d4e,
0x3d80,0x3d4ebd18,0xbd75bc95,0x3cac3d71,0x3d0ebd55,0xbd803b49,0x3d223d46,0x3c79bd78,0xbd6d3cc4,0x3d5c3d04,0xbbc9bd7f,0xbd3e3d2c,0x3d7b3c48,0xbcdbbd67,0xbcf13d62,0x3d7dbc16,
0x3d0ebd55,0xbd7dbc16,0x3c953d75,0x3d3ebd2c,0x3d353d35,0x3cacbd71,0xbd7f3bc9,0x3d043d5c,0xbc483d7b,0x3d78bc79,0xbd22bd46,0xbcdb3d67,0xbd6dbcc4,0x3b493d80,0x3d62bcf1,0xbd4ebd18,
0x3d7bbc48,0xbd18bd4e,0xbcf13d62,0x3d803b49,0x3d80,0x3d67bcdb,0xbd46bd22,0xbc793d78,0xbd553d0e,0x3d5c3d04,0x3bc9bd7f,0xbd713cac,0xbcc4bd6d,0xbd2c3d3e,0x3d753c95,0xbc16bd7d,
0xbcc43d6d,0x3d7d3c16,0xbbc9bd7f,0xbd713cac,0x3d0e3d55,0x3d2cbd3e,0xbd62bcf1,0xbc793d78,0xbd35bd35,0xbd043d5c,0x3d753c95,0x3b49bd80,0xbd7b3c48,0x3cdb3d67,0x3d46bd22,0xbd4ebd18,
0x3d6dbcc4,0xbd18bd4e,0xbd223d46,0x3d673cdb,0x3c48bd7b,0xbd803b49,0x3c953d75,0x3d5cbd04,0x3d80,0x3d78bc79,0xbcf1bd62,0xbd3e3d2c,0x3d553d0e,0x3cacbd71,0xbd7fbbc9,0x3c163d7d,
0x3d7b3c48,0x3c16bd7d,0xbd7fbbc9,0xbb493d80,0x3d6d3cc4,0x3cacbd71,0xbd75bc95,0xbc793d78,0x3d553d0e,0x3d04bd5c,0xbd62bcf1,0xbcdb3d67,0x3d353d35,0x3d2cbd3e,0xbd46bd22,0xbd183d4e,
0x3d0e3d55,0x3d4ebd18,0xbd22bd46,0xbd3e3d2c,0x3cc43d6d,0x3d67bcdb,0xbcf1bd62,0xbd5c3d04,0x3c483d7b,0x3d78bc79,0xbc95bd75,0xbd713cac,0x3d80,0x3d80bb49,0xbbc9bd7f,0xbd7d3c16,
0xbd800000,0x3d7d3c16,0xbd75bc95,0x3d673cdb,0xbd55bd0e,0x3d3e3d2c,0xbd22bd46,0x3d043d5c,0xbcc4bd6d,0x3c793d78,0xbbc9bd7f,0xbb493d80,0x3c48bd7b,0xbcac3d71,0x3cf1bd62,0xbd183d4e,
0x3d35bd35,0xbd4e3d18,0x3d62bcf1,0xbd713cac,0x3d7bbc48,0xbd803b49,0x3d7f3bc9,0xbd78bc79,0x3d6d3cc4,0xbd5cbd04,0x3d463d22,0xbd2cbd3e,0x3d0e3d55,0xbcdbbd67,0x3c953d75,0xbc16bd7d,
0xbc48bd7b,0xbc163d7d,0x3cf1bd62,0xbd3e3d2c,0xbd800000,0x3d713cac,0xbd46bd22,0x3d043d5c,0x3d0e3d55,0xbc79bd78,0xbbc93d7f,0x3cdbbd67,0x3d6dbcc4,0xbd803b49,0x3d753c95,0xbd4ebd18,
0xbd55bd0e,0x3d183d4e,0xbc95bd75,0xbb493d80,0xbd353d35,0x3d67bcdb,0xbd7f3bc9,0x3d783c79,0x3d7b3c48,0xbd5cbd04,0x3d223d46,0xbcacbd71,0x3cc4bd6d,0xbd2c3d3e,0x3d62bcf1,0xbd7d3c16,
0x3cc43d6d,0x3c16bd7d,0xbd223d46,0x3d71bcac,0xbd7bbc48,0x3d3e3d2c,0xbc95bd75,0xbc793d78,0xbd800000,0x3d5c3d04,0xbcf1bd62,0xbb493d80,0x3d0ebd55,0xbd673cdb,0x3d7f3bc9,0xbd4ebd18,
0xbd6dbcc4,0x3d183d4e,0xbbc9bd7f,0xbcdb3d67,0x3d55bd0e,0xbd803b49,0x3d623cf1,0xbd04bd5c,0x3d35bd35,0xbd783c79,0x3d753c95,0xbd2cbd3e,0x3c483d7b,0x3cacbd71,0xbd463d22,0x3d7dbc16,
0x3d55bd0e,0xbd7dbc16,0x3d223d46,0x3b49bd80,0xbd6d3cc4,0x3d713cac,0xbcf1bd62,0xbc793d78,0x3d7bbc48,0xbd5cbd04,0x3c953d75,0x3cdbbd67,0xbd800000,0x3d3e3d2c,0xbbc9bd7f,0xbd183d4e,
0x3c48bd7b,0xbd4e3d18,0x3d7f3bc9,0xbd2cbd3e,0xbcc43d6d,0x3d67bcdb,0xbd75bc95,0x3d043d5c,0x3d0ebd55,0xbd783c79,0x3d623cf1,0xbcacbd71,0xbd353d35,0x3d80bb49,0xbd46bd22,0x3c163d7d,
0x3d35bd35,0xbd7dbc16,0x3cf13d62,0x3cdbbd67,0xbd7b3c48,0x3d3e3d2c,0x3bc9bd7f,0xbd5c3d04,0x3d6d3cc4,0xbc79bd78,0xbd223d46,0x3d803b49,0xbd0ebd55,0xbcac3d71,0x3d75bc95,0xbd4ebd18,
0xbd800000,0x3d183d4e,0x3c95bd75,0xbd713cac,0x3d553d0e,0xbb49bd80,0xbd463d22,0x3d783c79,0xbcc4bd6d,0xbd043d5c,0x3d7fbbc9,0xbd2cbd3e,0xbc483d7b,0x3d67bcdb,0xbd62bcf1,0x3c163d7d,
0x3d553d0e,0x3c16bd7d,0xbd753c95,0x3d2c3d3e,0xbd353d35,0x3d713cac,0xbbc9bd7f,0xbd5c3d04,0xbd7bbc48,0x3c793d78,0x3d46bd22,0xbd67bcdb,0x3cc4bd6d,0xbd803b49,0x3cf13d62,0x3d18bd4e,
0x3c483d7b,0x3d4ebd18,0xbd62bcf1,0xbb493d80,0xbd800000,0x3cdb3d67,0x3d22bd46,0xbd78bc79,0xbd0ebd55,0xbd043d5c,0x3d7f3bc9,0xbcacbd71,0x3d6dbcc4,0xbd3ebd2c,0xbc953d75,0x3d7dbc16,
0xbd6dbcc4,0xbc163d7d,0x3d7fbbc9,0xbcacbd71,0xbd553d0e,0x3d3e3d2c,0x3cf1bd62,0xbd78bc79,0x3d35bd35,0xbd5cbd04,0xbc953d75,0x3d803b49,0xbc48bd7b,0xbd673cdb,0x3d223d46,0x3d18bd4e,
0x3cc43d6d,0x3d4ebd18,0xbd46bd22,0xbcdb3d67,0x3d7b3c48,0xbb49bd80,0xbd753c95,0x3d043d5c,0xbd800000,0x3c793d78,0x3d62bcf1,0xbd2cbd3e,0xbd0e3d55,0x3d713cac,0x3bc9bd7f,0xbd7d3c16,
0xbc483d7b,0x3d7d3c16,0x3bc9bd7f,0xbd80bb49,0xbcc43d6d,0x3d713cac,0x3c95bd75,0xbd78bc79,0xbd0e3d55,0x3d5c3d04,0x3cf1bd62,0xbd67bcdb,0xbd353d35,0x3d3e3d2c,0x3d22bd46,0xbd4ebd18,
0xbd553d0e,0x3d183d4e,0x3d46bd22,0xbd2cbd3e,0xbd6d3cc4,0x3cdb3d67,0x3d62bcf1,0xbd04bd5c,0xbd7b3c48,0x3c793d78,0x3d75bc95,0xbcacbd71,0xbd800000,0x3b493d80,0x3d7fbbc9,0xbc16bd7d,
0x3d80,0x3d7d3c16,0x3c95bd75,0xbd67bcdb,0xbd0e3d55,0x3d3e3d2c,0x3d46bd22,0xbd04bd5c,0xbd6d3cc4,0x3c793d78,0x3d7fbbc9,0x3b49bd80,0xbd7bbc48,0xbcac3d71,0x3d623cf1,0x3d18bd4e,
0xbd35bd35,0xbd4e3d18,0x3cf13d62,0x3d71bcac,0xbc48bd7b,0xbd803b49,0xbbc93d7f,0x3d783c79,0x3cc4bd6d,0xbd5cbd04,0xbd223d46,0x3d2c3d3e,0x3d55bd0e,0xbcdbbd67,0xbd753c95,0x3c163d7d,
0xbd7b3c48,0xbc163d7d,0x3d623cf1,0x3d3ebd2c,0x3d80,0x3d713cac,0x3d22bd46,0xbd04bd5c,0x3d55bd0e,0xbc79bd78,0xbd7fbbc9,0xbcdb3d67,0xbcc4bd6d,0xbd803b49,0xbc953d75,0x3d4e3d18,
0xbd0e3d55,0x3d183d4e,0x3d75bc95,0x3b49bd80,0x3d353d35,0x3d67bcdb,0xbbc9bd7f,0xbd78bc79,0x3c48bd7b,0xbd5cbd04,0xbd463d22,0x3cac3d71,0xbd6dbcc4,0xbd2c3d3e,0x3cf13d62,0x3d7dbc16,
0x3d6dbcc4,0x3c16bd7d,0xbd46bd22,0xbd713cac,0xbc483d7b,0x3d3e3d2c,0x3d75bc95,0x3c79bd78,0x3d80,0x3d5c3d04,0x3d62bcf1,0x3b49bd80,0xbd55bd0e,0xbd673cdb,0xbbc93d7f,0x3d4e3d18,
0xbcc43d6d,0x3d183d4e,0x3d7fbbc9,0x3cdbbd67,0xbd0ebd55,0xbd803b49,0xbcf13d62,0x3d043d5c,0xbd35bd35,0xbd783c79,0xbc953d75,0x3d2c3d3e,0x3d7bbc48,0x3cacbd71,0xbd22bd46,0xbd7d3c16,
0xbd0ebd55,0xbd7dbc16,0xbd463d22,0xbb493d80,0x3cc43d6d,0x3d713cac,0x3d62bcf1,0x3c79bd78,0xbc48bd7b,0xbd5cbd04,0xbd753c95,0xbcdb3d67,0x3d80,0x3d3e3d2c,0x3d7fbbc9,0x3d18bd4e,
0xbd7bbc48,0xbd4e3d18,0xbbc93d7f,0x3d2c3d3e,0x3d6d3cc4,0x3d67bcdb,0x3c95bd75,0xbd04bd5c,0xbd55bd0e,0xbd783c79,0xbcf13d62,0x3cac3d71,0x3d353d35,0x3d80bb49,0x3d22bd46,0xbc16bd7d,
0xbd35bd35,0xbd7dbc16,0xbd623cf1,0xbcdb3d67,0x3c483d7b,0x3d3e3d2c,0x3d7f3bc9,0x3d5cbd04,0x3cc4bd6d,0xbc79bd78,0xbd46bd22,0xbd80bb49,0xbd553d0e,0xbcac3d71,0x3c953d75,0x3d4e3d18,
0x3d80,0x3d183d4e,0x3d753c95,0x3d71bcac,0x3d0ebd55,0xbb49bd80,0xbd22bd46,0xbd78bc79,0xbd6d3cc4,0xbd043d5c,0x3bc93d7f,0x3d2c3d3e,0x3d7b3c48,0x3d67bcdb,0x3cf1bd62,0xbc16bd7d,
0x3d0ebd55,0x3c16bd7d,0xbc95bd75,0xbd2cbd3e,0x3d353d35,0x3d713cac,0x3d7fbbc9,0x3d5cbd04,0xbc483d7b,0x3c793d78,0x3d223d46,0x3d673cdb,0xbd6dbcc4,0xbd803b49,0xbd623cf1,0xbd183d4e,
0x3d7bbc48,0x3d4ebd18,0x3cf1bd62,0x3b49bd80,0x3d80,0x3cdb3d67,0x3d463d22,0x3d783c79,0xbd553d0e,0xbd043d5c,0xbbc93d7f,0x3cac3d71,0xbcc4bd6d,0xbd3ebd2c,0xbd75bc95,0xbd7d3c16,
0xbcc43d6d,0xbc163d7d,0x3bc93d7f,0x3cac3d71,0x3d0e3d55,0x3d3e3d2c,0x3d623cf1,0x3d783c79,0xbd35bd35,0xbd5cbd04,0xbd75bc95,0xbd80bb49,0xbd7b3c48,0xbd673cdb,0xbd463d22,0xbd183d4e,
0x3d6dbcc4,0x3d4ebd18,0x3d22bd46,0x3cdbbd67,0x3c48bd7b,0xbb49bd80,0xbc95bd75,0xbd04bd5c,0x3d80,0x3c793d78,0x3cf13d62,0x3d2c3d3e,0x3d553d0e,0x3d713cac,0x3d7f3bc9,0x3d7dbc16,
0x3d7b3c48,0x3d7d3c16,0x3d7f3bc9,0x3d803b49,0x3d6d3cc4,0x3d713cac,0x3d753c95,0x3d783c79,0x3d553d0e,0x3d5c3d04,0x3d623cf1,0x3d673cdb,0x3d353d35,0x3d3e3d2c,0x3d463d22,0x3d4e3d18,
0x3d0e3d55,0x3d183d4e,0x3d223d46,0x3d2c3d3e,0x3cc43d6d,0x3cdb3d67,0x3cf13d62,0x3d043d5c,0x3c483d7b,0x3c793d78,0x3c953d75,0x3cac3d71,0x3d80,0x3b493d80,0x3bc93d7f,0x3c163d7d,
0xbd800000,0xbc163d7d,0x3d753c95,0x3cdbbd67,0xbd55bd0e,0xbd2c3d3e,0x3d223d46,0x3d5cbd04,0xbcc4bd6d,0xbd783c79,0x3bc93d7f,0x3d803b49,0x3c48bd7b,0xbd71bcac,0xbcf13d62,0x3d4e3d18,
0x3d35bd35,0xbd18bd4e,0xbd623cf1,0x3cac3d71,0x3d7bbc48,0xbb49bd80,0xbd7fbbc9,0xbc793d78,0x3d6d3cc4,0x3d04bd5c,0xbd46bd22,0xbd3e3d2c,0x3d0e3d55,0x3d67bcdb,0xbc95bd75,0xbd7d3c16,
0xbc48bd7b,0xbd7dbc16,0xbcf13d62,0x3d2c3d3e,0xbd800000,0xbcac3d71,0x3d463d22,0x3d5cbd04,0x3d0e3d55,0x3d78bc79,0x3bc9bd7f,0xbd67bcdb,0x3d6dbcc4,0xbb49bd80,0xbd75bc95,0xbd183d4e,
0xbd55bd0e,0xbd4e3d18,0x3c953d75,0x3d803b49,0xbd353d35,0x3cdb3d67,0x3d7fbbc9,0x3c79bd78,0x3d7b3c48,0x3d04bd5c,0xbd22bd46,0xbd713cac,0x3cc4bd6d,0xbd3ebd2c,0xbd623cf1,0x3c163d7d,
0x3cc43d6d,0x3d7d3c16,0x3d22bd46,0xbcacbd71,0xbd7bbc48,0xbd2c3d3e,0x3c953d75,0x3d783c79,0xbd800000,0xbd043d5c,0x3cf13d62,0x3d803b49,0x3d0ebd55,0xbcdbbd67,0xbd7fbbc9,0xbd183d4e,
0xbd6dbcc4,0xbd4e3d18,0x3bc93d7f,0x3d673cdb,0x3d55bd0e,0xbb49bd80,0xbd62bcf1,0xbd5c3d04,0x3d35bd35,0xbc79bd78,0xbd75bc95,0xbd3e3d2c,0x3c483d7b,0x3d713cac,0x3d46bd22,0xbc16bd7d,
0x3d55bd0e,0x3c16bd7d,0xbd22bd46,0xbd80bb49,0xbd6d3cc4,0xbcac3d71,0x3cf13d62,0x3d783c79,0x3d7bbc48,0x3d04bd5c,0xbc95bd75,0xbd67bcdb,0xbd800000,0xbd2c3d3e,0x3bc93d7f,0x3d4e3d18,
0x3c48bd7b,0xbd18bd4e,0xbd7fbbc9,0xbd3e3d2c,0xbcc43d6d,0x3cdb3d67,0x3d753c95,0x3d5cbd04,0x3d0ebd55,0xbc79bd78,0xbd62bcf1,0xbd713cac,0xbd353d35,0x3b493d80,0x3d463d22,0x3d7dbc16,
0x3d35bd35,0x3c16bd7d,0xbcf1bd62,0xbd67bcdb,0xbd7b3c48,0xbd2c3d3e,0xbbc93d7f,0x3d043d5c,0x3d6d3cc4,0x3d78bc79,0x3d22bd46,0x3b49bd80,0xbd0ebd55,0xbd71bcac,0xbd753c95,0xbd183d4e,
0xbd800000,0xbd4e3d18,0xbc953d75,0x3cac3d71,0x3d553d0e,0x3d80bb49,0x3d46bd22,0x3c79bd78,0xbcc4bd6d,0xbd5cbd04,0xbd7f3bc9,0xbd3e3d2c,0xbc483d7b,0x3cdb3d67,0x3d623cf1,0x3d7dbc16,
0x3d553d0e,0x3d7d3c16,0x3d75bc95,0x3d3ebd2c,0xbd353d35,0xbcac3d71,0x3bc93d7f,0x3d043d5c,0xbd7bbc48,0xbd783c79,0xbd463d22,0xbcdb3d67,0x3cc4bd6d,0xbb49bd80,0xbcf1bd62,0xbd4ebd18,
0x3c483d7b,0x3d183d4e,0x3d623cf1,0x3d803b49,0xbd800000,0xbd673cdb,0xbd223d46,0xbc793d78,0xbd0ebd55,0xbd5cbd04,0xbd7fbbc9,0xbd713cac,0x3d6dbcc4,0x3d2cbd3e,0x3c95bd75,0xbc16bd7d,
0xbd6dbcc4,0xbd7dbc16,0xbd7f3bc9,0xbd713cac,0xbd553d0e,0xbd2c3d3e,0xbcf13d62,0xbc793d78,0x3d35bd35,0x3d04bd5c,0x3c95bd75,0x3b49bd80,0xbc48bd7b,0xbcdbbd67,0xbd22bd46,0xbd4ebd18,
0x3cc43d6d,0x3d183d4e,0x3d463d22,0x3d673cdb,0x3d7b3c48,0x3d80bb49,0x3d75bc95,0x3d5cbd04,0xbd800000,0xbd783c79,0xbd623cf1,0xbd3e3d2c,0xbd0e3d55,0xbcac3d71,0xbbc93d7f,0x3c163d7d,
0xbc483d7b,0xbc163d7d,0xbbc93d7f,0xbb493d80,0xbcc43d6d,0xbcac3d71,0xbc953d75,0xbc793d78,0xbd0e3d55,0xbd043d5c,0xbcf13d62,0xbcdb3d67,0xbd353d35,0xbd2c3d3e,0xbd223d46,0xbd183d4e,
0xbd553d0e,0xbd4e3d18,0xbd463d22,0xbd3e3d2c,0xbd6d3cc4,0xbd673cdb,0xbd623cf1,0xbd5c3d04,0xbd7b3c48,0xbd783c79,0xbd753c95,0xbd713cac,0xbd800000,0xbd803b49,0xbd7f3bc9,0xbd7d3c16,
0x3f003f00,0xbf003f00,0x3f003f00,0xbf003f00,0x3f003f00,0xbf003f00,0x3f003f00,0xbf003f00,0x3f003f00,0xbf003f00,0x3f003f00,0xbf003f00,0x3f003f00,0xbf003f00,0x3f003f00,0xbf003f00,
0x3eff3f00,0xbd490000,0x3ea23eb5,0xbec6beb5,0x3ef53efb,0xbe15bdc8,0x3e713e8e,0xbee2bed5,0x3ee23eed,0xbe71be44,0x3e153e44,0xbef5beed,0x3ec63ed5,0xbea2be8e,0x3d493dc8,0xbeffbefb,
0x3efb3f00,0xbdc80000,0xbdc80000,0xbefbbf00,0x3ed53eed,0xbe8ebe44,0xbe8ebe44,0xbed5beed,0x3e8e3eb5,0xbed5beb5,0xbed5beb5,0xbe8ebeb5,0x3dc83e44,0xbefbbeed,0xbefbbeed,0xbdc8be44,
0x3ef53f00,0xbe150000,0xbee2beb5,0xbe71beb5,0x3ea23ed5,0xbec6be8e,0xbeffbefb,0x3d49bdc8,0x3d493e44,0xbeffbeed,0xbec6beed,0x3ea23e44,0xbe71bdc8,0xbee2befb,0xbe15be8e,0x3ef53ed5,
0x3eed3f00,0xbe440000,0xbeedbf00,0x3e440000,0x3e443eb5,0xbeedbeb5,0xbe44beb5,0x3eed3eb5,0xbe440000,0xbeedbf00,0x3e440000,0x3eed3f00,0xbeedbeb5,0xbe44beb5,0x3eed3eb5,0x3e443eb5,
0x3ee23f00,0xbe710000,0xbe15beb5,0x3ef53eb5,0x3d493e8e,0xbeffbed5,0x3ea23dc8,0x3ec63efb,0xbec6be44,0xbea2beed,0x3eff3eed,0xbd493e44,0xbef5befb,0x3e15bdc8,0x3e713ed5,0xbee2be8e,
0x3ed53f00,0xbe8e0000,0x3e8e0000,0x3ed53f00,0xbdc83e44,0xbefbbeed,0x3efb3eed,0xbdc83e44,0xbefbbeb5,0xbdc8beb5,0x3dc83eb5,0xbefbbeb5,0xbe8ebeed,0x3ed53e44,0xbed5be44,0xbe8ebeed,
0x3ec63f00,0xbea20000,0x3eff3eb5,0x3d493eb5,0xbe713dc8,0xbee2befb,0x3e153ed5,0xbef5be8e,0xbef5beed,0x3e15be44,0xbee2be44,0xbe71beed,0x3d49be8e,0x3eff3ed5,0xbea2befb,0x3ec63dc8,
0x3f00,0xbf000000,0x3f00,0xbf000000,0xbf00,0x3f000000,0xbf00,0x3f000000,0x3f00,0xbf000000,0x3f00,0xbf000000,0xbf00,0x3f000000,0xbf00,0x3f000000,
0xbd493f00,0xbeff0000,0xbec63eb5,0xbea2beb5,0x3e15befb,0x3ef53dc8,0x3ee2be8e,0x3e713ed5,0xbe713eed,0xbee2be44,0xbef53e44,0xbe15beed,0x3ea2bed5,0x3ec63e8e,0x3effbdc8,0x3d493efb,
0xbdc83f00,0xbefb0000,0xbefb0000,0x3dc8bf00,0x3e8ebeed,0x3ed53e44,0x3ed53e44,0xbe8e3eed,0xbed53eb5,0xbe8ebeb5,0xbe8ebeb5,0x3ed5beb5,0x3efbbe44,0x3dc83eed,0x3dc83eed,0xbefb3e44,
0xbe153f00,0xbef50000,0xbe71beb5,0x3ee2beb5,0x3ec6bed5,0x3ea23e8e,0xbd493efb,0xbeff3dc8,0xbeff3e44,0xbd49beed,0x3ea2beed,0x3ec63e44,0x3ee23dc8,0xbe713efb,0xbef53e8e,0xbe15bed5,
0xbe443f00,0xbeed0000,0x3e44bf00,0x3eed0000,0x3eedbeb5,0x3e443eb5,0xbeed3eb5,0xbe44beb5,0xbeed0000,0x3e44bf00,0x3eed0000,0xbe443f00,0x3e443eb5,0xbeed3eb5,0xbe44beb5,0x3eedbeb5,
0xbe713f00,0xbee20000,0x3ef5beb5,0x3e153eb5,0x3effbe8e,0x3d493ed5,0xbec6bdc8,0x3ea2befb,0xbea2be44,0x3ec6beed,0xbd493eed,0xbeff3e44,0xbe153efb,0xbef53dc8,0x3ee2bed5,0x3e713e8e,
0xbe8e3f00,0xbed50000,0x3ed50000,0xbe8e3f00,0x3efbbe44,0xbdc83eed,0x3dc8beed,0x3efbbe44,0xbdc8beb5,0x3efbbeb5,0xbefb3eb5,0xbdc8beb5,0xbed53eed,0xbe8ebe44,0x3e8e3e44,0xbed53eed,
0xbea23f00,0xbec60000,0x3d493eb5,0xbeff3eb5,0x3ee2bdc8,0xbe713efb,0x3ef5bed5,0x3e153e8e,0x3e15beed,0x3ef5be44,0xbe71be44,0x3ee2beed,0xbeff3e8e,0x3d49bed5,0xbec63efb,0xbea2bdc8,
0x3eb53f00,0xbeb50000,0x3eb53f00,0xbeb50000,0xbeb50000,0xbeb5bf00,0xbeb50000,0xbeb5bf00,0xbeb5bf00,0x3eb50000,0xbeb5bf00,0x3eb50000,0x3eb50000,0x3eb53f00,0x3eb50000,0x3eb53f00,
0xbeff3f00,0x3d490000,0xbea23eb5,0x3ec6beb5,0xbef53efb,0x3e15bdc8,0xbe713e8e,0x3ee2bed5,0xbee23eed,0x3e71be44,0xbe153e44,0x3ef5beed,0xbec63ed5,0x3ea2be8e,0xbd493dc8,0x3effbefb,
0xbefb3f00,0x3dc80000,0x3dc80000,0x3efbbf00,0xbed53eed,0x3e8ebe44,0x3e8ebe44,0x3ed5beed,0xbe8e3eb5,0x3ed5beb5,0x3ed5beb5,0x3e8ebeb5,0xbdc83e44,0x3efbbeed,0x3efbbeed,0x3dc8be44,
0xbef53f00,0x3e150000,0x3ee2beb5,0x3e71beb5,0xbea23ed5,0x3ec6be8e,0x3effbefb,0xbd49bdc8,0xbd493e44,0x3effbeed,0x3ec6beed,0xbea23e44,0x3e71bdc8,0x3ee2befb,0x3e15be8e,0xbef53ed5,
0xbeed3f00,0x3e440000,0x3eedbf00,0xbe440000,0xbe443eb5,0x3eedbeb5,0x3e44beb5,0xbeed3eb5,0x3e440000,0x3eedbf00,0xbe440000,0xbeed3f00,0x3eedbeb5,0x3e44beb5,0xbeed3eb5,0xbe443eb5,
0xbee23f00,0x3e710000,0x3e15beb5,0xbef53eb5,0xbd493e8e,0x3effbed5,0xbea23dc8,0xbec63efb,0x3ec6be44,0x3ea2beed,0xbeff3eed,0x3d493e44,0x3ef5befb,0xbe15bdc8,0xbe713ed5,0x3ee2be8e,
0xbed53f00,0x3e8e0000,0xbe8e0000,0xbed53f00,0x3dc83e44,0x3efbbeed,0xbefb3eed,0x3dc83e44,0x3efbbeb5,0x3dc8beb5,0xbdc83eb5,0x3efbbeb5,0x3e8ebeed,0xbed53e44,0x3ed5be44,0x3e8ebeed,
0xbec63f00,0x3ea20000,0xbeff3eb5,0xbd493eb5,0x3e713dc8,0x3ee2befb,0xbe153ed5,0x3ef5be8e,0x3ef5beed,0xbe15be44,0x3ee2be44,0x3e71beed,0xbd49be8e,0xbeff3ed5,0x3ea2befb,0xbec63dc8,
0xbeb53f00,0xbeb50000,0xbeb53f00,0xbeb50000,0x3eb50000,0xbeb53f00,0x3eb50000,0xbeb53f00,0x3eb5bf00,0x3eb50000,0x3eb5bf00,0x3eb50000,0xbeb50000,0x3eb5bf00,0xbeb50000,0x3eb5bf00,
0x3d493f00,0x3eff0000,0x3ec63eb5,0x3ea2beb5,0xbe15befb,0xbef53dc8,0xbee2be8e,0xbe713ed5,0x3e713eed,0x3ee2be44,0x3ef53e44,0x3e15beed,0xbea2bed5,0xbec63e8e,0xbeffbdc8,0xbd493efb,
0x3dc83f00,0x3efb0000,0x3efb0000,0xbdc8bf00,0xbe8ebeed,0xbed53e44,0xbed53e44,0x3e8e3eed,0x3ed53eb5,0x3e8ebeb5,0x3e8ebeb5,0xbed5beb5,0xbefbbe44,0xbdc83eed,0xbdc83eed,0x3efb3e44,
0x3e153f00,0x3ef50000,0x3e71beb5,0xbee2beb5,0xbec6bed5,0xbea23e8e,0x3d493efb,0x3eff3dc8,0x3eff3e44,0x3d49beed,0xbea2beed,0xbec63e44,0xbee23dc8,0x3e713efb,0x3ef53e8e,0x3e15bed5,
0x3e443f00,0x3eed0000,0xbe44bf00,0xbeed0000,0xbeedbeb5,0xbe443eb5,0x3eed3eb5,0x3e44beb5,0x3eed0000,0xbe44bf00,0xbeed0000,0x3e443f00,0xbe443eb5,0x3eed3eb5,0x3e44beb5,0xbeedbeb5,
0x3e713f00,0x3ee20000,0xbef5beb5,0xbe153eb5,0xbeffbe8e,0xbd493ed5,0x3ec6bdc8,0xbea2befb,0x3ea2be44,0xbec6beed,0x3d493eed,0x3eff3e44,0x3e153efb,0x3ef53dc8,0xbee2bed5,0xbe713e8e,
0x3e8e3f00,0x3ed50000,0xbed50000,0x3e8e3f00,0xbefbbe44,0x3dc83eed,0xbdc8beed,0xbefbbe44,0x3dc8beb5,0xbefbbeb5,0x3efb3eb5,0x3dc8beb5,0x3ed53eed,0x3e8ebe44,0xbe8e3e44,0x3ed53eed,
0x3ea23f00,0x3ec60000,0xbd493eb5,0x3eff3eb5,0xbee2bdc8,0x3e713efb,0xbef5bed5,0xbe153e8e,0xbe15beed,0xbef5be44,0x3e71be44,0xbee2beed,0x3eff3e8e,0xbd49bed5,0x3ec63efb,0x3ea2bdc8,
0x3f003f00,0xbf003f00,0x3f003f00,0xbf003f00,0x3f003f00,0xbf003f00,0x3f003f00,0xbf003f00,0x3f003f00,0xbf003f00,0x3f003f00,0xbf003f00,0x3f003f00,0xbf003f00,0x3f003f00,0xbf003f00,
0xbd490000,0xbeffbf00,0xbec6beb5,0xbea2beb5,0xbe15bdc8,0xbef5befb,0xbee2bed5,0xbe71be8e,0xbe71be44,0xbee2beed,0xbef5beed,0xbe15be44,0xbea2be8e,0xbec6bed5,0xbeffbefb,0xbd49bdc8,
0xbefbbf00,0x3dc80000,0x3dc80000,0x3efb3f00,0xbed5beed,0x3e8e3e44,0x3e8e3e44,0x3ed53eed,0xbe8ebeb5,0x3ed53eb5,0x3ed53eb5,0x3e8e3eb5,0xbdc8be44,0x3efb3eed,0x3efb3eed,0x3dc83e44,
0x3e150000,0x3ef53f00,0x3e713eb5,0xbee2beb5,0x3ec63e8e,0x3ea23ed5,0xbd493dc8,0xbeffbefb,0x3eff3eed,0x3d493e44,0xbea2be44,0xbec6beed,0x3ee23efb,0xbe71bdc8,0xbef5bed5,0xbe15be8e,
0x3eed3f00,0xbe440000,0xbeedbf00,0x3e440000,0x3e443eb5,0xbeedbeb5,0xbe44beb5,0x3eed3eb5,0xbe440000,0xbeedbf00,0x3e440000,0x3eed3f00,0xbeedbeb5,0xbe44beb5,0x3eed3eb5,0x3e443eb5,
0xbe710000,0xbee2bf00,0x3ef53eb5,0x3e153eb5,0xbeffbed5,0xbd49be8e,0x3ec63efb,0xbea2bdc8,0xbea2beed,0x3ec63e44,0xbd493e44,0xbeffbeed,0x3e15bdc8,0x3ef53efb,0xbee2be8e,0xbe71bed5,
0xbed5bf00,0x3e8e0000,0xbe8e0000,0xbed5bf00,0x3dc8be44,0x3efb3eed,0xbefbbeed,0x3dc8be44,0x3efb3eb5,0x3dc83eb5,0xbdc8beb5,0x3efb3eb5,0x3e8e3eed,0xbed5be44,0x3ed53e44,0x3e8e3eed,
0x3ea20000,0x3ec63f00,0xbd49beb5,0x3eff3eb5,0x3ee23efb,0xbe713dc8,0x3ef53e8e,0x3e153ed5,0xbe153e44,0xbef5beed,0x3e713eed,0xbee2be44,0xbeffbed5,0x3d49be8e,0xbec6bdc8,0xbea2befb,
0x3f00,0xbf000000,0x3f00,0xbf000000,0xbf00,0x3f000000,0xbf00,0x3f000000,0x3f00,0xbf000000,0x3f00,0xbf000000,0xbf00,0x3f000000,0xbf00,0x3f000000,
0xbeff0000,0x3d49bf00,0xbea2beb5,0x3ec6beb5,0x3ef53dc8,0xbe153efb,0x3e713ed5,0xbee23e8e,0xbee2be44,0x3e71beed,0xbe15beed,0x3ef5be44,0x3ec63e8e,0xbea23ed5,0x3d493efb,0xbeff3dc8,
0x3dc8bf00,0x3efb0000,0x3efb0000,0xbdc83f00,0xbe8e3eed,0xbed5be44,0xbed5be44,0x3e8ebeed,0x3ed5beb5,0x3e8e3eb5,0x3e8e3eb5,0xbed53eb5,0xbefb3e44,0xbdc8beed,0xbdc8beed,0x3efbbe44,
0x3ef50000,0xbe153f00,0xbee23eb5,0xbe71beb5,0xbea2be8e,0x3ec6bed5,0x3effbdc8,0xbd493efb,0x3d493eed,0xbeff3e44,0xbec6be44,0x3ea2beed,0x3e71befb,0x3ee23dc8,0x3e153ed5,0xbef53e8e,
0xbe443f00,0xbeed0000,0x3e44bf00,0x3eed0000,0x3eedbeb5,0x3e443eb5,0xbeed3eb5,0xbe44beb5,0xbeed0000,0x3e44bf00,0x3eed0000,0xbe443f00,0x3e443eb5,0xbeed3eb5,0xbe44beb5,0x3eedbeb5,
0xbee20000,0x3e71bf00,0x3e153eb5,0xbef53eb5,0x3d493ed5,0xbeff3e8e,0x3ea2befb,0x3ec63dc8,0x3ec6beed,0x3ea23e44,0xbeff3e44,0x3d49beed,0xbef53dc8,0x3e15befb,0x3e713e8e,0xbee23ed5,
0x3e8ebf00,0x3ed50000,0xbed50000,0x3e8ebf00,0xbefb3e44,0x3dc8beed,0xbdc83eed,0xbefb3e44,0x3dc83eb5,0xbefb3eb5,0x3efbbeb5,0x3dc83eb5,0x3ed5beed,0x3e8e3e44,0xbe8ebe44,0x3ed5beed,
0x3ec60000,0xbea23f00,0x3effbeb5,0x3d493eb5,0x3e71befb,0x3ee2bdc8,0xbe15be8e,0x3ef5bed5,0xbef53e44,0x3e15beed,0xbee23eed,0xbe71be44,0xbd493ed5,0xbeff3e8e,0x3ea23dc8,0xbec63efb,
0x3eb53f00,0xbeb50000,0x3eb53f00,0xbeb50000,0xbeb50000,0xbeb5bf00,0xbeb50000,0xbeb5bf00,0xbeb5bf00,0x3eb50000,0xbeb5bf00,0x3eb50000,0x3eb50000,0x3eb53f00,0x3eb50000,0x3eb53f00,
0x3d490000,0x3effbf00,0x3ec6beb5,0x3ea2beb5,0x3e15bdc8,0x3ef5befb,0x3ee2bed5,0x3e71be8e,0x3e71be44,0x3ee2beed,0x3ef5beed,0x3e15be44,0x3ea2be8e,0x3ec6bed5,0x3effbefb,0x3d49bdc8,
0x3efbbf00,0xbdc80000,0xbdc80000,0xbefb3f00,0x3ed5beed,0xbe8e3e44,0xbe8e3e44,0xbed53eed,0x3e8ebeb5,0xbed53eb5,0xbed53eb5,0xbe8e3eb5,0x3dc8be44,0xbefb3eed,0xbefb3eed,0xbdc83e44,
0xbe150000,0xbef53f00,0xbe713eb5,0x3ee2beb5,0xbec63e8e,0xbea23ed5,0x3d493dc8,0x3effbefb,0xbeff3eed,0xbd493e44,0x3ea2be44,0x3ec6beed,0xbee23efb,0x3e71bdc8,0x3ef5bed5,0x3e15be8e,
0xbeed3f00,0x3e440000,0x3eedbf00,0xbe440000,0xbe443eb5,0x3eedbeb5,0x3e44beb5,0xbeed3eb5,0x3e440000,0x3eedbf00,0xbe440000,0xbeed3f00,0x3eedbeb5,0x3e44beb5,0xbeed3eb5,0xbe443eb5,
0x3e710000,0x3ee2bf00,0xbef53eb5,0xbe153eb5,0x3effbed5,0x3d49be8e,0xbec63efb,0x3ea2bdc8,0x3ea2beed,0xbec63e44,0x3d493e44,0x3effbeed,0xbe15bdc8,0xbef53efb,0x3ee2be8e,0x3e71bed5,
0x3ed5bf00,0xbe8e0000,0x3e8e0000,0x3ed5bf00,0xbdc8be44,0xbefb3eed,0x3efbbeed,0xbdc8be44,0xbefb3eb5,0xbdc83eb5,0x3dc8beb5,0xbefb3eb5,0xbe8e3eed,0x3ed5be44,0xbed53e44,0xbe8e3eed,
0xbea20000,0xbec63f00,0x3d49beb5,0xbeff3eb5,0xbee23efb,0x3e713dc8,0xbef53e8e,0xbe153ed5,0x3e153e44,0x3ef5beed,0xbe713eed,0x3ee2be44,0x3effbed5,0xbd49be8e,0x3ec6bdc8,0x3ea2befb,
0xbeb53f00,0xbeb50000,0xbeb53f00,0xbeb50000,0x3eb50000,0xbeb53f00,0x3eb50000,0xbeb53f00,0x3eb5bf00,0x3eb50000,0x3eb5bf00,0x3eb50000,0xbeb50000,0x3eb5bf00,0xbeb50000,0x3eb5bf00,
0x3eff0000,0xbd49bf00,0x3ea2beb5,0xbec6beb5,0xbef53dc8,0x3e153efb,0xbe713ed5,0x3ee23e8e,0x3ee2be44,0xbe71beed,0x3e15beed,0xbef5be44,0xbec63e8e,0x3ea23ed5,0xbd493efb,0x3eff3dc8,
0xbdc8bf00,0xbefb0000,0xbefb0000,0x3dc83f00,0x3e8e3eed,0x3ed5be44,0x3ed5be44,0xbe8ebeed,0xbed5beb5,0xbe8e3eb5,0xbe8e3eb5,0x3ed53eb5,0x3efb3e44,0x3dc8beed,0x3dc8beed,0xbefbbe44,
0xbef50000,0x3e153f00,0x3ee23eb5,0x3e71beb5,0x3ea2be8e,0xbec6bed5,0xbeffbdc8,0x3d493efb,0xbd493eed,0x3eff3e44,0x3ec6be44,0xbea2beed,0xbe71befb,0xbee23dc8,0xbe153ed5,0x3ef53e8e,
0x3e443f00,0x3eed0000,0xbe44bf00,0xbeed0000,0xbeedbeb5,0xbe443eb5,0x3eed3eb5,0x3e44beb5,0x3eed0000,0xbe44bf00,0xbeed0000,0x3e443f00,0xbe443eb5,0x3eed3eb5,0x3e44beb5,0xbeedbeb5,
0x3ee20000,0xbe71bf00,0xbe153eb5,0x3ef53eb5,0xbd493ed5,0x3eff3e8e,0xbea2befb,0xbec63dc8,0xbec6beed,0xbea23e44,0x3eff3e44,0xbd49beed,0x3ef53dc8,0xbe15befb,0xbe713e8e,0x3ee23ed5,
0xbe8ebf00,0xbed50000,0x3ed50000,0xbe8ebf00,0x3efb3e44,0xbdc8beed,0x3dc83eed,0x3efb3e44,0xbdc83eb5,0x3efb3eb5,0xbefbbeb5,0xbdc83eb5,0xbed5beed,0xbe8e3e44,0x3e8ebe44,0xbed5beed,
0xbec60000,0x3ea23f00,0xbeffbeb5,0xbd493eb5,0xbe71befb,0xbee2bdc8,0x3e15be8e,0xbef5bed5,0x3ef53e44,0xbe15beed,0x3ee23eed,0x3e71be44,0x3d493ed5,0x3eff3e8e,0xbea23dc8,0x3ec63efb,
0x3f003f00,0xbf003f00,0x3f003f00,0xbf003f00,0x3f003f00,0xbf003f00,0x3f003f00,0xbf003f00,0x3f003f00,0xbf003f00,0x3f003f00,0xbf003f00,0x3f003f00,0xbf003f00,0x3f003f00,0xbf003f00,
0xbeffbf00,0x3d490000,0xbea2beb5,0x3ec63eb5,0xbef5befb,0x3e153dc8,0xbe71be8e,0x3ee23ed5,0xbee2beed,0x3e713e44,0xbe15be44,0x3ef53eed,0xbec6bed5,0x3ea23e8e,0xbd49bdc8,0x3eff3efb,
0x3efb3f00,0xbdc80000,0xbdc80000,0xbefbbf00,0x3ed53eed,0xbe8ebe44,0xbe8ebe44,0xbed5beed,0x3e8e3eb5,0xbed5beb5,0xbed5beb5,0xbe8ebeb5,0x3dc83e44,0xbefbbeed,0xbefbbeed,0xbdc8be44,
0xbef5bf00,0x3e150000,0x3ee23eb5,0x3e713eb5,0xbea2bed5,0x3ec63e8e,0x3eff3efb,0xbd493dc8,0xbd49be44,0x3eff3eed,0x3ec63eed,0xbea2be44,0x3e713dc8,0x3ee23efb,0x3e153e8e,0xbef5bed5,
0x3eed3f00,0xbe440000,0xbeedbf00,0x3e440000,0x3e443eb5,0xbeedbeb5,0xbe44beb5,0x3eed3eb5,0xbe440000,0xbeedbf00,0x3e440000,0x3eed3f00,0xbeedbeb5,0xbe44beb5,0x3eed3eb5,0x3e443eb5,
0xbee2bf00,0x3e710000,0x3e153eb5,0xbef5beb5,0xbd49be8e,0x3eff3ed5,0xbea2bdc8,0xbec6befb,0x3ec63e44,0x3ea23eed,0xbeffbeed,0x3d49be44,0x3ef53efb,0xbe153dc8,0xbe71bed5,0x3ee23e8e,
0x3ed53f00,0xbe8e0000,0x3e8e0000,0x3ed53f00,0xbdc83e44,0xbefbbeed,0x3efb3eed,0xbdc83e44,0xbefbbeb5,0xbdc8beb5,0x3dc83eb5,0xbefbbeb5,0xbe8ebeed,0x3ed53e44,0xbed5be44,0xbe8ebeed,
0xbec6bf00,0x3ea20000,0xbeffbeb5,0xbd49beb5,0x3e71bdc8,0x3ee23efb,0xbe15bed5,0x3ef53e8e,0x3ef53eed,0xbe153e44,0x3ee23e44,0x3e713eed,0xbd493e8e,0xbeffbed5,0x3ea23efb,0xbec6bdc8,
0x3f00,0xbf000000,0x3f00,0xbf000000,0xbf00,0x3f000000,0xbf00,0x3f000000,0x3f00,0xbf000000,0x3f00,0xbf000000,0xbf00,0x3f000000,0xbf00,0x3f000000,
0x3d49bf00,0x3eff0000,0x3ec6beb5,0x3ea23eb5,0xbe153efb,0xbef5bdc8,0xbee23e8e,0xbe71bed5,0x3e71beed,0x3ee23e44,0x3ef5be44,0x3e153eed,0xbea23ed5,0xbec6be8e,0xbeff3dc8,0xbd49befb,
0xbdc83f00,0xbefb0000,0xbefb0000,0x3dc8bf00,0x3e8ebeed,0x3ed53e44,0x3ed53e44,0xbe8e3eed,0xbed53eb5,0xbe8ebeb5,0xbe8ebeb5,0x3ed5beb5,0x3efbbe44,0x3dc83eed,0x3dc83eed,0xbefb3e44,
0x3e15bf00,0x3ef50000,0x3e713eb5,0xbee23eb5,0xbec63ed5,0xbea2be8e,0x3d49befb,0x3effbdc8,0x3effbe44,0x3d493eed,0xbea23eed,0xbec6be44,0xbee2bdc8,0x3e71befb,0x3ef5be8e,0x3e153ed5,
0xbe443f00,0xbeed0000,0x3e44bf00,0x3eed0000,0x3eedbeb5,0x3e443eb5,0xbeed3eb5,0xbe44beb5,0xbeed0000,0x3e44bf00,0x3eed0000,0xbe443f00,0x3e443eb5,0xbeed3eb5,0xbe44beb5,0x3eedbeb5,
0x3e71bf00,0x3ee20000,0xbef53eb5,0xbe15beb5,0xbeff3e8e,0xbd49bed5,0x3ec63dc8,0xbea23efb,0x3ea23e44,0xbec63eed,0x3d49beed,0x3effbe44,0x3e15befb,0x3ef5bdc8,0xbee23ed5,0xbe71be8e,
0xbe8e3f00,0xbed50000,0x3ed50000,0xbe8e3f00,0x3efbbe44,0xbdc83eed,0x3dc8beed,0x3efbbe44,0xbdc8beb5,0x3efbbeb5,0xbefb3eb5,0xbdc8beb5,0xbed53eed,0xbe8ebe44,0x3e8e3e44,0xbed53eed,
0x3ea2bf00,0x3ec60000,0xbd49beb5,0x3effbeb5,0xbee23dc8,0x3e71befb,0xbef53ed5,0xbe15be8e,0xbe153eed,0xbef53e44,0x3e713e44,0xbee23eed,0x3effbe8e,0xbd493ed5,0x3ec6befb,0x3ea23dc8,
0x3eb53f00,0xbeb50000,0x3eb53f00,0xbeb50000,0xbeb50000,0xbeb5bf00,0xbeb50000,0xbeb5bf00,0xbeb5bf00,0x3eb50000,0xbeb5bf00,0x3eb50000,0x3eb50000,0x3eb53f00,0x3eb50000,0x3eb53f00,
0x3effbf00,0xbd490000,0x3ea2beb5,0xbec63eb5,0x3ef5befb,0xbe153dc8,0x3e71be8e,0xbee23ed5,0x3ee2beed,0xbe713e44,0x3e15be44,0xbef53eed,0x3ec6bed5,0xbea23e8e,0x3d49bdc8,0xbeff3efb,
0xbefb3f00,0x3dc80000,0x3dc80000,0x3efbbf00,0xbed53eed,0x3e8ebe44,0x3e8ebe44,0x3ed5beed,0xbe8e3eb5,0x3ed5beb5,0x3ed5beb5,0x3e8ebeb5,0xbdc83e44,0x3efbbeed,0x3efbbeed,0x3dc8be44,
0x3ef5bf00,0xbe150000,0xbee23eb5,0xbe713eb5,0x3ea2bed5,0xbec63e8e,0xbeff3efb,0x3d493dc8,0x3d49be44,0xbeff3eed,0xbec63eed,0x3ea2be44,0xbe713dc8,0xbee23efb,0xbe153e8e,0x3ef5bed5,
0xbeed3f00,0x3e440000,0x3eedbf00,0xbe440000,0xbe443eb5,0x3eedbeb5,0x3e44beb5,0xbeed3eb5,0x3e440000,0x3eedbf00,0xbe440000,0xbeed3f00,0x3eedbeb5,0x3e44beb5,0xbeed3eb5,0xbe443eb5,
0x3ee2bf00,0xbe710000,0xbe153eb5,0x3ef5beb5,0x3d49be8e,0xbeff3ed5,0x3ea2bdc8,0x3ec6befb,0xbec63e44,0xbea23eed,0x3effbeed,0xbd49be44,0xbef53efb,0x3e153dc8,0x3e71bed5,0xbee23e8e,
0xbed53f00,0x3e8e0000,0xbe8e0000,0xbed53f00,0x3dc83e44,0x3efbbeed,0xbefb3eed,0x3dc83e44,0x3efbbeb5,0x3dc8beb5,0xbdc83eb5,0x3efbbeb5,0x3e8ebeed,0xbed53e44,0x3ed5be44,0x3e8ebeed,
0x3ec6bf00,0xbea20000,0x3effbeb5,0x3d49beb5,0xbe71bdc8,0xbee23efb,0x3e15bed5,0xbef53e8e,0xbef53eed,0x3e153e44,0xbee23e44,0xbe713eed,0x3d493e8e,0x3effbed5,0xbea23efb,0x3ec6bdc8,
0xbeb53f00,0xbeb50000,0xbeb53f00,0xbeb50000,0x3eb50000,0xbeb53f00,0x3eb50000,0xbeb53f00,0x3eb5bf00,0x3eb50000,0x3eb5bf00,0x3eb50000,0xbeb50000,0x3eb5bf00,0xbeb50000,0x3eb5bf00,
0xbd49bf00,0xbeff0000,0xbec6beb5,0xbea23eb5,0x3e153efb,0x3ef5bdc8,0x3ee23e8e,0x3e71bed5,0xbe71beed,0xbee23e44,0xbef5be44,0xbe153eed,0x3ea23ed5,0x3ec6be8e,0x3eff3dc8,0x3d49befb,
0x3dc83f00,0x3efb0000,0x3efb0000,0xbdc8bf00,0xbe8ebeed,0xbed53e44,0xbed53e44,0x3e8e3eed,0x3ed53eb5,0x3e8ebeb5,0x3e8ebeb5,0xbed5beb5,0xbefbbe44,0xbdc83eed,0xbdc83eed,0x3efb3e44,
0xbe15bf00,0xbef50000,0xbe713eb5,0x3ee23eb5,0x3ec63ed5,0x3ea2be8e,0xbd49befb,0xbeffbdc8,0xbeffbe44,0xbd493eed,0x3ea23eed,0x3ec6be44,0x3ee2bdc8,0xbe71befb,0xbef5be8e,0xbe153ed5,
0x3e443f00,0x3eed0000,0xbe44bf00,0xbeed0000,0xbeedbeb5,0xbe443eb5,0x3eed3eb5,0x3e44beb5,0x3eed0000,0xbe44bf00,0xbeed0000,0x3e443f00,0xbe443eb5,0x3eed3eb5,0x3e44beb5,0xbeedbeb5,
0xbe71bf00,0xbee20000,0x3ef53eb5,0x3e15beb5,0x3eff3e8e,0x3d49bed5,0xbec63dc8,0x3ea23efb,0xbea23e44,0x3ec63eed,0xbd49beed,0xbeffbe44,0xbe15befb,0xbef5bdc8,0x3ee23ed5,0x3e71be8e,
0x3e8e3f00,0x3ed50000,0xbed50000,0x3e8e3f00,0xbefbbe44,0x3dc83eed,0xbdc8beed,0xbefbbe44,0x3dc8beb5,0xbefbbeb5,0x3efb3eb5,0x3dc8beb5,0x3ed53eed,0x3e8ebe44,0xbe8e3e44,0x3ed53eed,
0xbea2bf00,0xbec60000,0x3d49beb5,0xbeffbeb5,0x3ee23dc8,0xbe71befb,0x3ef53ed5,0x3e15be8e,0x3e153eed,0x3ef53e44,0xbe713e44,0x3ee23eed,0xbeffbe8e,0x3d493ed5,0xbec6befb,0xbea23dc8,
0x3f003f00,0xbf003f00,0x3f003f00,0xbf003f00,0x3f003f00,0xbf003f00,0x3f003f00,0xbf003f00,0x3f003f00,0xbf003f00,0x3f003f00,0xbf003f00,0x3f003f00,0xbf003f00,0x3f003f00,0xbf003f00,
0x3d490000,0x3eff3f00,0x3ec63eb5,0x3ea23eb5,0x3e153dc8,0x3ef53efb,0x3ee23ed5,0x3e713e8e,0x3e713e44,0x3ee23eed,0x3ef53eed,0x3e153e44,0x3ea23e8e,0x3ec63ed5,0x3eff3efb,0x3d493dc8,
0xbefbbf00,0x3dc80000,0x3dc80000,0x3efb3f00,0xbed5beed,0x3e8e3e44,0x3e8e3e44,0x3ed53eed,0xbe8ebeb5,0x3ed53eb5,0x3ed53eb5,0x3e8e3eb5,0xbdc8be44,0x3efb3eed,0x3efb3eed,0x3dc83e44,
0xbe150000,0xbef5bf00,0xbe71beb5,0x3ee23eb5,0xbec6be8e,0xbea2bed5,0x3d49bdc8,0x3eff3efb,0xbeffbeed,0xbd49be44,0x3ea23e44,0x3ec63eed,0xbee2befb,0x3e713dc8,0x3ef53ed5,0x3e153e8e,
0x3eed3f00,0xbe440000,0xbeedbf00,0x3e440000,0x3e443eb5,0xbeedbeb5,0xbe44beb5,0x3eed3eb5,0xbe440000,0xbeedbf00,0x3e440000,0x3eed3f00,0xbeedbeb5,0xbe44beb5,0x3eed3eb5,0x3e443eb5,
0x3e710000,0x3ee23f00,0xbef5beb5,0xbe15beb5,0x3eff3ed5,0x3d493e8e,0xbec6befb,0x3ea23dc8,0x3ea23eed,0xbec6be44,0x3d49be44,0x3eff3eed,0xbe153dc8,0xbef5befb,0x3ee23e8e,0x3e713ed5,
0xbed5bf00,0x3e8e0000,0xbe8e0000,0xbed5bf00,0x3dc8be44,0x3efb3eed,0xbefbbeed,0x3dc8be44,0x3efb3eb5,0x3dc83eb5,0xbdc8beb5,0x3efb3eb5,0x3e8e3eed,0xbed5be44,0x3ed53e44,0x3e8e3eed,
0xbea20000,0xbec6bf00,0x3d493eb5,0xbeffbeb5,0xbee2befb,0x3e71bdc8,0xbef5be8e,0xbe15bed5,0x3e15be44,0x3ef53eed,0xbe71beed,0x3ee23e44,0x3eff3ed5,0xbd493e8e,0x3ec63dc8,0x3ea23efb,
0x3f00,0xbf000000,0x3f00,0xbf000000,0xbf00,0x3f000000,0xbf00,0x3f000000,0x3f00,0xbf000000,0x3f00,0xbf000000,0xbf00,0x3f000000,0xbf00,0x3f000000,
0x3eff0000,0xbd493f00,0x3ea23eb5,0xbec63eb5,0xbef5bdc8,0x3e15befb,0xbe71bed5,0x3ee2be8e,0x3ee23e44,0xbe713eed,0x3e153eed,0xbef53e44,0xbec6be8e,0x3ea2bed5,0xbd49befb,0x3effbdc8,
0x3dc8bf00,0x3efb0000,0x3efb0000,0xbdc83f00,0xbe8e3eed,0xbed5be44,0xbed5be44,0x3e8ebeed,0x3ed5beb5,0x3e8e3eb5,0x3e8e3eb5,0xbed53eb5,0xbefb3e44,0xbdc8beed,0xbdc8beed,0x3efbbe44,
0xbef50000,0x3e15bf00,0x3ee2beb5,0x3e713eb5,0x3ea23e8e,0xbec63ed5,0xbeff3dc8,0x3d49befb,0xbd49beed,0x3effbe44,0x3ec63e44,0xbea23eed,0xbe713efb,0xbee2bdc8,0xbe15bed5,0x3ef5be8e,
0xbe443f00,0xbeed0000,0x3e44bf00,0x3eed0000,0x3eedbeb5,0x3e443eb5,0xbeed3eb5,0xbe44beb5,0xbeed0000,0x3e44bf00,0x3eed0000,0xbe443f00,0x3e443eb5,0xbeed3eb5,0xbe44beb5,0x3eedbeb5,
0x3ee20000,0xbe713f00,0xbe15beb5,0x3ef5beb5,0xbd49bed5,0x3effbe8e,0xbea23efb,0xbec6bdc8,0xbec63eed,0xbea2be44,0x3effbe44,0xbd493eed,0x3ef5bdc8,0xbe153efb,0xbe71be8e,0x3ee2bed5,
0x3e8ebf00,0x3ed50000,0xbed50000,0x3e8ebf00,0xbefb3e44,0x3dc8beed,0xbdc83eed,0xbefb3e44,0x3dc83eb5,0xbefb3eb5,0x3efbbeb5,0x3dc83eb5,0x3ed5beed,0x3e8e3e44,0xbe8ebe44,0x3ed5beed,
0xbec60000,0x3ea2bf00,0xbeff3eb5,0xbd49beb5,0xbe713efb,0xbee23dc8,0x3e153e8e,0xbef53ed5,0x3ef5be44,0xbe153eed,0x3ee2beed,0x3e713e44,0x3d49bed5,0x3effbe8e,0xbea2bdc8,0x3ec6befb,
0x3eb53f00,0xbeb50000,0x3eb53f00,0xbeb50000,0xbeb50000,0xbeb5bf00,0xbeb50000,0xbeb5bf00,0xbeb5bf00,0x3eb50000,0xbeb5bf00,0x3eb50000,0x3eb50000,0x3eb53f00,0x3eb50000,0x3eb53f00,
0xbd490000,0xbeff3f00,0xbec63eb5,0xbea23eb5,0xbe153dc8,0xbef53efb,0xbee23ed5,0xbe713e8e,0xbe713e44,0xbee23eed,0xbef53eed,0xbe153e44,0xbea23e8e,0xbec63ed5,0xbeff3efb,0xbd493dc8,
0x3efbbf00,0xbdc80000,0xbdc80000,0xbefb3f00,0x3ed5beed,0xbe8e3e44,0xbe8e3e44,0xbed53eed,0x3e8ebeb5,0xbed53eb5,0xbed53eb5,0xbe8e3eb5,0x3dc8be44,0xbefb3eed,0xbefb3eed,0xbdc83e44,
0x3e150000,0x3ef5bf00,0x3e71beb5,0xbee23eb5,0x3ec6be8e,0x3ea2bed5,0xbd49bdc8,0xbeff3efb,0x3effbeed,0x3d49be44,0xbea23e44,0xbec63eed,0x3ee2befb,0xbe713dc8,0xbef53ed5,0xbe153e8e,
0xbeed3f00,0x3e440000,0x3eedbf00,0xbe440000,0xbe443eb5,0x3eedbeb5,0x3e44beb5,0xbeed3eb5,0x3e440000,0x3eedbf00,0xbe440000,0xbeed3f00,0x3eedbeb5,0x3e44beb5,0xbeed3eb5,0xbe443eb5,
0xbe710000,0xbee23f00,0x3ef5beb5,0x3e15beb5,0xbeff3ed5,0xbd493e8e,0x3ec6befb,0xbea23dc8,0xbea23eed,0x3ec6be44,0xbd49be44,0xbeff3eed,0x3e153dc8,0x3ef5befb,0xbee23e8e,0xbe713ed5,
0x3ed5bf00,0xbe8e0000,0x3e8e0000,0x3ed5bf00,0xbdc8be44,0xbefb3eed,0x3efbbeed,0xbdc8be44,0xbefb3eb5,0xbdc83eb5,0x3dc8beb5,0xbefb3eb5,0xbe8e3eed,0x3ed5be44,0xbed53e44,0xbe8e3eed,
0x3ea20000,0x3ec6bf00,0xbd493eb5,0x3effbeb5,0x3ee2befb,0xbe71bdc8,0x3ef5be8e,0x3e15bed5,0xbe15be44,0xbef53eed,0x3e71beed,0xbee23e44,0xbeff3ed5,0x3d493e8e,0xbec63dc8,0xbea23efb,
0xbeb53f00,0xbeb50000,0xbeb53f00,0xbeb50000,0x3eb50000,0xbeb53f00,0x3eb50000,0xbeb53f00,0x3eb5bf00,0x3eb50000,0x3eb5bf00,0x3eb50000,0xbeb50000,0x3eb5bf00,0xbeb50000,0x3eb5bf00,
0xbeff0000,0x3d493f00,0xbea23eb5,0x3ec63eb5,0x3ef5bdc8,0xbe15befb,0x3e71bed5,0xbee2be8e,0xbee23e44,0x3e713eed,0xbe153eed,0x3ef53e44,0x3ec6be8e,0xbea2bed5,0x3d49befb,0xbeffbdc8,
0xbdc8bf00,0xbefb0000,0xbefb0000,0x3dc83f00,0x3e8e3eed,0x3ed5be44,0x3ed5be44,0xbe8ebeed,0xbed5beb5,0xbe8e3eb5,0xbe8e3eb5,0x3ed53eb5,0x3efb3e44,0x3dc8beed,0x3dc8beed,0xbefbbe44,
0x3ef50000,0xbe15bf00,0xbee2beb5,0xbe713eb5,0xbea23e8e,0x3ec63ed5,0x3eff3dc8,0xbd49befb,0x3d49beed,0xbeffbe44,0xbec63e44,0x3ea23eed,0x3e713efb,0x3ee2bdc8,0x3e15bed5,0xbef5be8e,
0x3e443f00,0x3eed0000,0xbe44bf00,0xbeed0000,0xbeedbeb5,0xbe443eb5,0x3eed3eb5,0x3e44beb5,0x3eed0000,0xbe44bf00,0xbeed0000,0x3e443f00,0xbe443eb5,0x3eed3eb5,0x3e44beb5,0xbeedbeb5,
0xbee20000,0x3e713f00,0x3e15beb5,0xbef5beb5,0x3d49bed5,0xbeffbe8e,0x3ea23efb,0x3ec6bdc8,0x3ec63eed,0x3ea2be44,0xbeffbe44,0x3d493eed,0xbef5bdc8,0x3e153efb,0x3e71be8e,0xbee2bed5,
0xbe8ebf00,0xbed50000,0x3ed50000,0xbe8ebf00,0x3efb3e44,0xbdc8beed,0x3dc83eed,0x3efb3e44,0xbdc83eb5,0x3efb3eb5,0xbefbbeb5,0xbdc83eb5,0xbed5beed,0xbe8e3e44,0x3e8ebe44,0xbed5beed,
0x3ec60000,0xbea2bf00,0x3eff3eb5,0x3d49beb5,0x3e713efb,0x3ee23dc8,0xbe153e8e,0x3ef53ed5,0xbef5be44,0x3e153eed,0xbee2beed,0xbe713e44,0xbd49bed5,0xbeffbe8e,0x3ea2bdc8,0xbec6befb,
0x3f800000,0x0,0x3f800000,0x0,0x3f800000,0x0,0x3f800000,0x0,0x3f800000,0x0,0x3f800000,0x0,0x3f800000,0x0,0x3f800000,0x0,
0x3f800000,0x0,0x3f7fec43,0xbcc90ab0,0x3f7fb10f,0xbd48fb30,0x3f7f4e6d,0xbd96a905,0x3f7ec46d,0xbdc8bd36,0x3f7e1324,0xbdfab273,0x3f7d3aac,0xbe164083,0x3f7c3b28,0xbe2f10a2,
0x3f800000,0x0,0x3f7ffec4,0xbbc90f88,0x3f7ffb11,0xbc490e90,0x3f7ff4e6,0xbc96c9b6,0x3f7fec43,0xbcc90ab0,0x3f7fe129,0xbcfb49ba,0x3f7fd397,0xbd16c32c,0x3f7fc38f,0xbd2fe007,
0x3f800000,0x0,0x3f7fe129,0xbcfb49ba,0x3f7f84ab,0xbd7b2b74,0x3f7eea9d,0xbdbc3ac3,0x3f7e1324,0xbdfab273,0x3f7cfe73,0xbe1c76de,0x3f7baccd,0xbe3b6ecf,0x3f7a1e84,0xbe5a3997,
0x3f800000,0x0,0x3f7ffb11,0xbc490e90,0x3f7fec43,0xbcc90ab0,0x3f7fd397,0xbd16c32c,0x3f7fb10f,0xbd48fb30,0x3f7f84ab,0xbd7b2b74,0x3f7f4e6d,0xbd96a905,0x3f7f0e58,0xbdafb680,
0x3f800000,0x0,0x3f7fd397,0xbd16c32c,0x3f7f4e6d,0xbd96a905,0x3f7e70b0,0xbde1bc2e,0x3f7d3aac,0xbe164083,0x3f7baccd,0xbe3b6ecf,0x3f79c79d,0xbe605c13,0x3f778bc5,0xbe827dc0,
0x3f800000,0x0,0x3f7ff4e6,0xbc96c9b6,0x3f7fd397,0xbd16c32c,0x3f7f9c18,0xbd621469,0x3f7f4e6d,0xbd96a905,0x3f7eea9d,0xbdbc3ac3,0x3f7e70b0,0xbde1bc2e,0x3f7de0b1,0xbe039502,
0x3f800000,0x0,0x3f7fc38f,0xbd2fe007,0x3f7f0e58,0xbdafb680,0x3f7de0b1,0xbe039502,0x3f7c3b28,0xbe2f10a2,0x3f7a1e84,0xbe5a3997,0x3f778bc5,0xbe827dc0,0x3f748422,0xbe97a117,
0x3f800000,0x0,0x3f7fb10f,0xbd48fb30,0x3f7ec46d,0xbdc8bd36,0x3f7d3aac,0xbe164083,0x3f7b14be,0xbe47c5c2,0x3f7853f8,0xbe78cfcc,0x3f74fa0b,0xbe94a031,0x3f710908,0xbeac7cd4,
0x3f800000,0x0,0x3f7f4e6d,0xbd96a905,0x3f7d3aac,0xbe164083,0x3f79c79d,0xbe605c13,0x3f74fa0b,0xbe94a031,0x3f6ed89e,0xbeb8442a,0x3f676bd8,0xbedae880,0x3f5ebe05,0xbefc5d27,
0x3f800000,0x0,0x3f7f9c18,0xbd621469,0x3f7e70b0,0xbde1bc2e,0x3f7c7eb0,0xbe28defc,0x3f79c79d,0xbe605c13,0x3f764d97,0xbe8b9507,0x3f721352,0xbea68f12,0x3f6d1c1d,0xbec1071e,
0x3f800000,0x0,0x3f7f2f9d,0xbda3308c,0x3f7cbfc9,0xbe22abb6,0x3f78b47b,0xbe72b651,0x3f731447,0xbea09ae5,0x3f6be858,0xbec6d529,0x3f633c5a,0xbeebcbbb,0x3f591e6a,0xbf07a136,
0x3f800000,0x0,0x3f7f84ab,0xbd7b2b74,0x3f7e1324,0xbdfab273,0x3f7baccd,0xbe3b6ecf,0x3f7853f8,0xbe78cfcc,0x3f740bdd,0xbe9aa086,0x3f6ed89e,0xbeb8442a,0x3f68bf3c,0xbed53641,
0x3f800000,0x0,0x3f7f0e58,0xbdafb680,0x3f7c3b28,0xbe2f10a2,0x3f778bc5,0xbe827dc0,0x3f710908,0xbeac7cd4,0x3f68bf3c,0xbed53641,0x3f5ebe05,0xbefc5d27,0x3f531849,0xbf10d3cd,
0x3f800000,0x0,0x3f7f6ac7,0xbd8a200a,0x3f7dabcc,0xbe09cf86,0x3f7ac516,0xbe4dee60,0x3f76ba07,0xbe888e93,0x3f718f57,0xbea986c4,0x3f6b4b0c,0xbec9b953,0x3f63f473,0xbee900b7,
0x3f800000,0x0,0x3f7eea9d,0xbdbc3ac3,0x3f7baccd,0xbe3b6ecf,0x3f764d97,0xbe8b9507,0x3f6ed89e,0xbeb8442a,0x3f655e0b,0xbee363fa,0x3f59f26a,0xbf064b82,0x3f4cae79,0xbf19c200,
0x3f800000,0x0,0x3f7ec46d,0xbdc8bd36,0x3f7b14be,0xbe47c5c2,0x3f74fa0b,0xbe94a031,0x3f6c835e,0xbec3ef15,0x3f61c598,0xbef15aea,0x3f54db31,0xbf0e39da,0x3f45e403,0xbf226799,
0x3f800000,0x0,0x3f7e1324,0xbdfab273,0x3f7853f8,0xbe78cfcc,0x3f6ed89e,0xbeb8442a,0x3f61c598,0xbef15aea,0x3f514d3d,0xbf13682a,0x3f3daef9,0xbf2beb4a,0x3f273656,0xbf41d870,
0x3f800000,0x0,0x3f7e9bc9,0xbdd53db9,0x3f7a7302,0xbe541501,0x3f73913f,0xbe9d9e78,0x3f6a09a7,0xbecf7bca,0x3f5df6be,0xbeff17b2,0x3f4f7a1f,0xbf15f6d9,0x3f3ebc1b,0xbf2ac082,
0x3f800000,0x0,0x3f7de0b1,0xbe039502,0x3f778bc5,0xbe827dc0,0x3f6d1c1d,0xbec1071e,0x3f5ebe05,0xbefc5d27,0x3f4cae79,0xbf19c200,0x3f373a23,0xbf32c8c9,0x3f1ebc12,0xbf48d8b3,
0x3f800000,0x0,0x3f7e70b0,0xbde1bc2e,0x3f79c79d,0xbe605c13,0x3f721352,0xbea68f12,0x3f676bd8,0xbedae880,0x3f59f26a,0xbf064b82,0x3f49d112,0xbf1d7fd1,0x3f373a23,0xbf32c8c9,
0x3f800000,0x0,0x3f7dabcc,0xbe09cf86,0x3f76ba07,0xbe888e93,0x3f6b4b0c,0xbec9b953,0x3f5b941a,0xbf039c3d,0x3f47de65,0xbf1ff6cb,0x3f3085bb,0xbf396842,0x3f15f6d9,0xbf4f7a1f,
0x3f800000,0x0,0x3f7e4323,0xbdee3876,0x3f791298,0xbe6c9a7f,0x3f708066,0xbeaf713a,0x3f64aa59,0xbee63375,0x3f55b993,0xbf0cead0,0x3f43e200,0xbf24d225,0x3f2f61a5,0xbf3a7ca4,
0x3f800000,0x0,0x3f7d7474,0xbe1008b7,0x3f75dec6,0xbe8e9a22,0x3f696591,0xbed25a09,0x3f584853,0xbf08f59b,0x3f42de29,0xbf26050a,0x3f299415,0xbf3fc767,0x3f0cead0,0xbf55b993,
0x3f800000,0x0,0x3f7d3aac,0xbe164083,0x3f74fa0b,0xbe94a031,0x3f676bd8,0xbedae880,0x3f54db31,0xbf0e39da,0x3f3daef9,0xbf2beb4a,0x3f226799,0xbf45e403,0x3f039c3d,0xbf5b941a,
0x3f800000,0x0,0x3f7c3b28,0xbe2f10a2,0x3f710908,0xbeac7cd4,0x3f5ebe05,0xbefc5d27,0x3f45e403,0xbf226799,0x3f273656,0xbf41d870,0x3f039c3d,0xbf5b941a,0x3eb8442a,0xbf6ed89e,
0x3f800000,0x0,0x3f7cfe73,0xbe1c76de,0x3f740bdd,0xbe9aa086,0x3f655e0b,0xbee363fa,0x3f514d3d,0xbf13682a,0x3f385216,0xbf31a81d,0x3f1b02c6,0xbf4bbbf8,0x3ef41f07,0xbf6106f2,
0x3f800000,0x0,0x3f7bf531,0xbe354098,0x3f6ff573,0xbeb263ef,0x3f5c61c7,0xbf0242b1,0x3f41d870,0xbf273656,0x3f212ff9,0xbf46e22a,0x3ef6e0cb,0xbf604621,0x3ea395c5,0xbf7294f8,
0x3f800000,0x0,0x3f7cbfc9,0xbe22abb6,0x3f731447,0xbea09ae5,0x3f633c5a,0xbeebcbbb,0x3f4d9f02,0xbf187fc0,0x3f32c8c9,0xbf373a23,0x3f13682a,0xbf514d3d,0x3ee0924f,0xbf660f88,
0x3f800000,0x0,0x3f7baccd,0xbe3b6ecf,0x3f6ed89e,0xbeb8442a,0x3f59f26a,0xbf064b82,0x3f3daef9,0xbf2beb4a,0x3f1b02c6,0xbf4bbbf8,0x3ee63375,0xbf64aa59,0x3e8e9a22,0xbf75dec6,
0x3f800000,0x0,0x3f7c7eb0,0xbe28defc,0x3f721352,0xbea68f12,0x3f6106f2,0xbef41f07,0x3f49d112,0xbf1d7fd1,0x3f2d1469,0xbf3ca003,0x3f0b9a6b,0xbf5695e5,0x3ecc9b8b,0xbf6aab7b,
0x3f800000,0x0,0x3f7b61fc,0xbe419b37,0x3f6db293,0xbebe1d4a,0x3f577026,0xbf0a48ad,0x3f396842,0xbf3085bb,0x3f14b039,0xbf5064af,0x3ed53641,0xbf68bf3c,0x3e72b651,0xbf78b47b,
0x3f800000,0x0,0x3f800000,0x0,0x3f800000,0x0,0x3f800000,0x0,0x3f800000,0x0,0x3f800000,0x0,0x3f800000,0x0,0x3f800000,0x0,
0x3f7b14be,0xbe47c5c2,0x3f79c79d,0xbe605c13,0x3f7853f8,0xbe78cfcc,0x3f76ba07,0xbe888e93,0x3f74fa0b,0xbe94a031,0x3f731447,0xbea09ae5,0x3f710908,0xbeac7cd4,0x3f6ed89e,0xbeb8442a,
0x3f7fb10f,0xbd48fb30,0x3f7f9c18,0xbd621469,0x3f7f84ab,0xbd7b2b74,0x3f7f6ac7,0xbd8a200a,0x3f7f4e6d,0xbd96a905,0x3f7f2f9d,0xbda3308c,0x3f7f0e58,0xbdafb680,0x3f7eea9d,0xbdbc3ac3,
0x3f7853f8,0xbe78cfcc,0x3f764d97,0xbe8b9507,0x3f740bdd,0xbe9aa086,0x3f718f57,0xbea986c4,0x3f6ed89e,0xbeb8442a,0x3f6be858,0xbec6d529,0x3f68bf3c,0xbed53641,0x3f655e0b,0xbee363fa,
0x3f7ec46d,0xbdc8bd36,0x3f7e70b0,0xbde1bc2e,0x3f7e1324,0xbdfab273,0x3f7dabcc,0xbe09cf86,0x3f7d3aac,0xbe164083,0x3f7cbfc9,0xbe22abb6,0x3f7c3b28,0xbe2f10a2,0x3f7baccd,0xbe3b6ecf,
0x3f74fa0b,0xbe94a031,0x3f721352,0xbea68f12,0x3f6ed89e,0xbeb8442a,0x3f6b4b0c,0xbec9b953,0x3f676bd8,0xbedae880,0x3f633c5a,0xbeebcbbb,0x3f5ebe05,0xbefc5d27,0x3f59f26a,0xbf064b82,
0x3f7d3aac,0xbe164083,0x3f7c7eb0,0xbe28defc,0x3f7baccd,0xbe3b6ecf,0x3f7ac516,0xbe4dee60,0x3f79c79d,0xbe605c13,0x3f78b47b,0xbe72b651,0x3f778bc5,0xbe827dc0,0x3f764d97,0xbe8b9507,
0x3f710908,0xbeac7cd4,0x3f6d1c1d,0xbec1071e,0x3f68bf3c,0xbed53641,0x3f63f473,0xbee900b7,0x3f5ebe05,0xbefc5d27,0x3f591e6a,0xbf07a136,0x3f531849,0xbf10d3cd,0x3f4cae79,0xbf19c200,
0x3f6c835e,0xbec3ef15,0x3f676bd8,0xbedae880,0x3f61c598,0xbef15aea,0x3f5b941a,0xbf039c3d,0x3f54db31,0xbf0e39da,0x3f4d9f02,0xbf187fc0,0x3f45e403,0xbf226799,0x3f3daef9,0xbf2beb4a,
0x3f54db31,0xbf0e39da,0x3f49d112,0xbf1d7fd1,0x3f3daef9,0xbf2beb4a,0x3f3085bb,0xbf396842,0x3f226799,0xbf45e403,0x3f13682a,0xbf514d3d,0x3f039c3d,0xbf5b941a,0x3ee63375,0xbf64aa59,
0x3f676bd8,0xbedae880,0x3f6106f2,0xbef41f07,0x3f59f26a,0xbf064b82,0x3f5233c6,0xbf121eb0,0x3f49d112,0xbf1d7fd1,0x3f40d0da,0xbf286605,0x3f373a23,0xbf32c8c9,0x3f2d1469,0xbf3ca003,
0x3f4d9f02,0xbf187fc0,0x3f40d0da,0xbf286605,0x3f32c8c9,0xbf373a23,0x3f239da9,0xbf44e3f5,0x3f13682a,0xbf514d3d,0x3f0242b1,0xbf5c61c7,0x3ee0924f,0xbf660f88,0x3ebb31a0,0xbf6e46be,
0x3f61c598,0xbef15aea,0x3f59f26a,0xbf064b82,0x3f514d3d,0xbf13682a,0x3f47de65,0xbf1ff6cb,0x3f3daef9,0xbf2beb4a,0x3f32c8c9,0xbf373a23,0x3f273656,0xbf41d870,0x3f1b02c6,0xbf4bbbf8,
0x3f45e403,0xbf226799,0x3f373a23,0xbf32c8c9,0x3f273656,0xbf41d870,0x3f15f6d9,0xbf4f7a1f,0x3f039c3d,0xbf5b941a,0x3ee0924f,0xbf660f88,0x3eb8442a,0xbf6ed89e,0x3e8e9a22,0xbf75dec6,
0x3f5b941a,0xbf039c3d,0x3f5233c6,0xbf121eb0,0x3f47de65,0xbf1ff6cb,0x3f3ca003,0xbf2d1469,0x3f3085bb,0xbf396842,0x3f239da9,0xbf44e3f5,0x3f15f6d9,0xbf4f7a1f,0x3f07a136,0xbf591e6a,
0x3f3daef9,0xbf2beb4a,0x3f2d1469,0xbf3ca003,0x3f1b02c6,0xbf4bbbf8,0x3f07a136,0xbf591e6a,0x3ee63375,0xbf64aa59,0x3ebb31a0,0xbf6e46be,0x3e8e9a22,0xbf75dec6,0x3e419b37,0xbf7b61fc,
0x3f3504f3,0xbf3504f3,0x3f226799,0xbf45e403,0x3f0e39da,0xbf54db31,0x3ef15aea,0xbf61c598,0x3ec3ef15,0xbf6c835e,0x3e94a031,0xbf74fa0b,0x3e47c5c2,0xbf7b14be,0x3dc8bd36,0xbf7ec46d,
0x3f0e39da,0xbf54db31,0x3ee63375,0xbf64aa59,0x3eac7cd4,0xbf710908,0x3e605c13,0xbf79c79d,0x3dc8bd36,0xbf7ec46d,0xbcc90ab0,0xbf7fec43,0xbe164083,0xbf7d3aac,0xbe888e93,0xbf76ba07,
0x3f2beb4a,0xbf3daef9,0x3f173c07,0xbf4e8d90,0x3f00e7e4,0xbf5d2d53,0x3ed25a09,0xbf696591,0x3ea09ae5,0xbf731447,0x3e5a3997,0xbf7a1e84,0x3de1bc2e,0xbf7e70b0,0x3bc90f88,0xbf7ffec4,
0x3f039c3d,0xbf5b941a,0x3ecc9b8b,0xbf6aab7b,0x3e8e9a22,0xbf75dec6,0x3e1c76de,0xbf7cfe73,0x3cc90ab0,0xbf7fec43,0xbdd53db9,0xbf7e9bc9,0xbe6c9a7f,0xbf791298,0xbeb554ec,0xbf6f6830,
0x3f226799,0xbf45e403,0x3f0b9a6b,0xbf5695e5,0x3ee63375,0xbf64aa59,0x3eb263ef,0xbf6ff573,0x3e78cfcc,0xbf7853f8,0x3e09cf86,0xbf7dabcc,0x3cc90ab0,0xbf7fec43,0xbdafb680,0xbf7f0e58,
0x3ef15aea,0xbf61c598,0x3eb263ef,0xbf6ff573,0x3e605c13,0xbf79c79d,0x3dafb680,0xbf7f0e58,0xbd48fb30,0xbf7fb10f,0xbe3b6ecf,0xbf7baccd,0xbea09ae5,0xbf731447,0xbee0924f,0xbf660f88,
0x3f187fc0,0xbf4d9f02,0x3eff17b2,0xbf5df6be,0x3ec9b953,0xbf6b4b0c,0x3e919ddd,0xbf756d97,0x3e2f10a2,0xbf7c3b28,0x3d621469,0xbf7f9c18,0xbd7b2b74,0xbf7f84ab,0xbe354098,0xbf7bf531,
0x3edae880,0xbf676bd8,0x3e97a117,0xbf748422,0x3e22abb6,0xbf7cbfc9,0x3c96c9b6,0xbf7ff4e6,0xbdfab273,0xbf7e1324,0xbe8586ce,0xbf772417,0xbec9b953,0xbf6b4b0c,0xbf04f484,0xbf5ac450,
0x3ec3ef15,0xbf6c835e,0x3e78cfcc,0xbf7853f8,0x3dc8bd36,0xbf7ec46d,0xbd48fb30,0xbf7fb10f,0xbe47c5c2,0xbf7b14be,0xbeac7cd4,0xbf710908,0xbef15aea,0xbf61c598,0xbf187fc0,0xbf4d9f02,
0x3e47c5c2,0xbf7b14be,0x3cc90ab0,0xbf7fec43,0xbe164083,0xbf7d3aac,0xbea09ae5,0xbf731447,0xbef15aea,0xbf61c598,0xbf1d7fd1,0xbf49d112,0xbf3daef9,0xbf2beb4a,0xbf584853,0xbf08f59b,
0x3eac7cd4,0xbf710908,0x3e419b37,0xbf7b61fc,0x3d16c32c,0xbf7fd397,0xbdee3876,0xbf7e4323,0xbe888e93,0xbf76ba07,0xbed25a09,0xbf696591,0xbf0b9a6b,0xbf5695e5,0xbf2ac082,0xbf3ebc1b,
0x3e164083,0xbf7d3aac,0xbcfb49ba,0xbf7fe129,0xbe541501,0xbf7a7302,0xbec1071e,0xbf6d1c1d,0xbf08f59b,0xbf584853,0xbf2d1469,0xbf3ca003,0xbf4bbbf8,0xbf1b02c6,0xbf63f473,0xbee900b7,
0x3e94a031,0xbf74fa0b,0x3e09cf86,0xbf7dabcc,0xbcc90ab0,0xbf7fec43,0xbe3b6ecf,0xbf7baccd,0xbeac7cd4,0xbf710908,0xbef6e0cb,0xbf604621,0xbf1d7fd1,0xbf49d112,0xbf3b8f3b,0xbf2e3bde,
0x3dc8bd36,0xbf7ec46d,0xbdafb680,0xbf7f0e58,0xbe888e93,0xbf76ba07,0xbee0924f,0xbf660f88,0xbf187fc0,0xbf4d9f02,0xbf3b8f3b,0xbf2e3bde,0xbf584853,0xbf08f59b,0xbf6db293,0xbebe1d4a,
0x3e78cfcc,0xbf7853f8,0x3da3308c,0xbf7f2f9d,0xbdafb680,0xbf7f0e58,0xbe7ee6e1,0xbf77f110,0xbecf7bca,0xbf6a09a7,0xbf0cead0,0xbf55b993,0xbf2e3bde,0xbf3b8f3b,0xbf4ac77f,0xbf1c420c,
0x3d48fb30,0xbf7fb10f,0xbe1008b7,0xbf7d7474,0xbea68f12,0xbf721352,0xbeff17b2,0xbf5df6be,0xbf273656,0xbf41d870,0xbf48d8b3,0xbf1ebc12,0xbf633c5a,0xbeebcbbb,0xbf756d97,0xbe919ddd,
0x3f800000,0x0,0x3f800000,0x0,0x3f800000,0x0,0x3f800000,0x0,0x3f800000,0x0,0x3f800000,0x0,0x3f800000,0x0,0x3f800000,0x0,
0x3f6c835e,0xbec3ef15,0x3f6a09a7,0xbecf7bca,0x3f676bd8,0xbedae880,0x3f64aa59,0xbee63375,0x3f61c598,0xbef15aea,0x3f5ebe05,0xbefc5d27,0x3f5b941a,0xbf039c3d,0x3f584853,0xbf08f59b,
0x3f7ec46d,0xbdc8bd36,0x3f7e9bc9,0xbdd53db9,0x3f7e70b0,0xbde1bc2e,0x3f7e4323,0xbdee3876,0x3f7e1324,0xbdfab273,0x3f7de0b1,0xbe039502,0x3f7dabcc,0xbe09cf86,0x3f7d7474,0xbe1008b7,
0x3f61c598,0xbef15aea,0x3f5df6be,0xbeff17b2,0x3f59f26a,0xbf064b82,0x3f55b993,0xbf0cead0,0x3f514d3d,0xbf13682a,0x3f4cae79,0xbf19c200,0x3f47de65,0xbf1ff6cb,0x3f42de29,0xbf26050a,
0x3f7b14be,0xbe47c5c2,0x3f7a7302,0xbe541501,0x3f79c79d,0xbe605c13,0x3f791298,0xbe6c9a7f,0x3f7853f8,0xbe78cfcc,0x3f778bc5,0xbe827dc0,0x3f76ba07,0xbe888e93,0x3f75dec6,0xbe8e9a22,
0x3f54db31,0xbf0e39da,0x3f4f7a1f,0xbf15f6d9,0x3f49d112,0xbf1d7fd1,0x3f43e200,0xbf24d225,0x3f3daef9,0xbf2beb4a,0x3f373a23,0xbf32c8c9,0x3f3085bb,0xbf396842,0x3f299415,0xbf3fc767,
0x3f74fa0b,0xbe94a031,0x3f73913f,0xbe9d9e78,0x3f721352,0xbea68f12,0x3f708066,0xbeaf713a,0x3f6ed89e,0xbeb8442a,0x3f6d1c1d,0xbec1071e,0x3f6b4b0c,0xbec9b953,0x3f696591,0xbed25a09,
0x3f45e403,0xbf226799,0x3f3ebc1b,0xbf2ac082,0x3f373a23,0xbf32c8c9,0x3f2f61a5,0xbf3a7ca4,0x3f273656,0xbf41d870,0x3f1ebc12,0xbf48d8b3,0x3f15f6d9,0xbf4f7a1f,0x3f0cead0,0xbf55b993,
0x3f3504f3,0xbf3504f3,0x3f2beb4a,0xbf3daef9,0x3f226799,0xbf45e403,0x3f187fc0,0xbf4d9f02,0x3f0e39da,0xbf54db31,0x3f039c3d,0xbf5b941a,0x3ef15aea,0xbf61c598,0x3edae880,0xbf676bd8,
0x3ec3ef15,0xbf6c835e,0x3ea09ae5,0xbf731447,0x3e78cfcc,0xbf7853f8,0x3e2f10a2,0xbf7c3b28,0x3dc8bd36,0xbf7ec46d,0x3cc90ab0,0xbf7fec43,0xbd48fb30,0xbf7fb10f,0xbdfab273,0xbf7e1324,
0x3f226799,0xbf45e403,0x3f173c07,0xbf4e8d90,0x3f0b9a6b,0xbf5695e5,0x3eff17b2,0xbf5df6be,0x3ee63375,0xbf64aa59,0x3ecc9b8b,0xbf6aab7b,0x3eb263ef,0xbf6ff573,0x3e97a117,0xbf748422,
0x3e94a031,0xbf74fa0b,0x3e5a3997,0xbf7a1e84,0x3e09cf86,0xbf7dabcc,0x3d621469,0xbf7f9c18,0xbcc90ab0,0xbf7fec43,0xbdd53db9,0xbf7e9bc9,0xbe3b6ecf,0xbf7baccd,0xbe8586ce,0xbf772417,
0x3f0e39da,0xbf54db31,0x3f00e7e4,0xbf5d2d53,0x3ee63375,0xbf64aa59,0x3ec9b953,0xbf6b4b0c,0x3eac7cd4,0xbf710908,0x3e8e9a22,0xbf75dec6,0x3e605c13,0xbf79c79d,0x3e22abb6,0xbf7cbfc9,
0x3e47c5c2,0xbf7b14be,0x3de1bc2e,0xbf7e70b0,0x3cc90ab0,0xbf7fec43,0xbd7b2b74,0xbf7f84ab,0xbe164083,0xbf7d3aac,0xbe6c9a7f,0xbf791298,0xbea09ae5,0xbf731447,0xbec9b953,0xbf6b4b0c,
0x3ef15aea,0xbf61c598,0x3ed25a09,0xbf696591,0x3eb263ef,0xbf6ff573,0x3e919ddd,0xbf756d97,0x3e605c13,0xbf79c79d,0x3e1c76de,0xbf7cfe73,0x3dafb680,0xbf7f0e58,0x3c96c9b6,0xbf7ff4e6,
0x3dc8bd36,0xbf7ec46d,0x3bc90f88,0xbf7ffec4,0xbdafb680,0xbf7f0e58,0xbe354098,0xbf7bf531,0xbe888e93,0xbf76ba07,0xbeb554ec,0xbf6f6830,0xbee0924f,0xbf660f88,0xbf04f484,0xbf5ac450,
0x0,0xbf800000,0xbdc8bd36,0xbf7ec46d,0xbe47c5c2,0xbf7b14be,0xbe94a031,0xbf74fa0b,0xbec3ef15,0xbf6c835e,0xbef15aea,0xbf61c598,0xbf0e39da,0xbf54db31,0xbf226799,0xbf45e403,
0xbec3ef15,0xbf6c835e,0xbefc5d27,0xbf5ebe05,0xbf187fc0,0xbf4d9f02,0xbf3085bb,0xbf396842,0xbf45e403,0xbf226799,0xbf584853,0xbf08f59b,0xbf676bd8,0xbedae880,0xbf731447,0xbea09ae5,
0xbdc8bd36,0xbf7ec46d,0xbe4dee60,0xbf7ac516,0xbe9aa086,0xbf740bdd,0xbecc9b8b,0xbf6aab7b,0xbefc5d27,0xbf5ebe05,0xbf14b039,0xbf5064af,0xbf299415,0xbf3fc767,0xbf3ca003,0xbf2d1469,
0xbef15aea,0xbf61c598,0xbf14b039,0xbf5064af,0xbf2e3bde,0xbf3b8f3b,0xbf44e3f5,0xbf239da9,0xbf584853,0xbf08f59b,0xbf6816a8,0xbed8106b,0xbf740bdd,0xbe9aa086,0xbf7bf531,0xbe354098,
0xbe47c5c2,0xbf7b14be,0xbe9aa086,0xbf740bdd,0xbecf7bca,0xbf6a09a7,0xbf00e7e4,0xbf5d2d53,0xbf187fc0,0xbf4d9f02,0xbf2e3bde,0xbf3b8f3b,0xbf41d870,0xbf273656,0xbf531849,0xbf10d3cd,
0xbf0e39da,0xbf54db31,0xbf299415,0xbf3fc767,0xbf41d870,0xbf273656,0xbf5695e5,0xbf0b9a6b,0xbf676bd8,0xbedae880,0xbf740bdd,0xbe9aa086,0xbf7c3b28,0xbe2f10a2,0xbf7fd397,0xbd16c32c,
0xbe94a031,0xbf74fa0b,0xbecc9b8b,0xbf6aab7b,0xbf00e7e4,0xbf5d2d53,0xbf19c200,0xbf4cae79,0xbf3085bb,0xbf396842,0xbf44e3f5,0xbf239da9,0xbf5695e5,0xbf0b9a6b,0xbf655e0b,0xbee363fa,
0xbf226799,0xbf45e403,0xbf3ca003,0xbf2d1469,0xbf531849,0xbf10d3cd,0xbf655e0b,0xbee363fa,0xbf731447,0xbea09ae5,0xbf7bf531,0xbe354098,0xbf7fd397,0xbd16c32c,0xbf7e9bc9,0x3dd53db9,
0xbf3504f3,0xbf3504f3,0xbf4d9f02,0xbf187fc0,0xbf61c598,0xbef15aea,0xbf710908,0xbeac7cd4,0xbf7b14be,0xbe47c5c2,0xbf7fb10f,0xbd48fb30,0xbf7ec46d,0x3dc8bd36,0xbf7853f8,0x3e78cfcc,
0xbf6c835e,0xbec3ef15,0xbf79c79d,0xbe605c13,0xbf7fb10f,0xbd48fb30,0xbf7e1324,0x3dfab273,0xbf74fa0b,0x3e94a031,0xbf64aa59,0x3ee63375,0xbf4d9f02,0x3f187fc0,0xbf3085bb,0x3f396842,
0xbf45e403,0xbf226799,0xbf5c61c7,0xbf0242b1,0xbf6db293,0xbebe1d4a,0xbf796e4e,0xbe667c66,0xbf7f4e6d,0xbd96a905,0xbf7f2f9d,0x3da3308c,0xbf791298,0x3e6c9a7f,0xbf6d1c1d,0x3ec1071e,
0xbf74fa0b,0xbe94a031,0xbf7e4323,0xbdee3876,0xbf7f84ab,0x3d7b2b74,0xbf78b47b,0x3e72b651,0xbf6a09a7,0x3ecf7bca,0xbf53fac3,0x3f0f8784,0xbf373a23,0x3f32c8c9,0xbf14b039,0x3f5064af,
0xbf54db31,0xbf0e39da,0xbf68bf3c,0xbed53641,0xbf76ba07,0xbe888e93,0xbf7e70b0,0xbde1bc2e,0xbf7fb10f,0x3d48fb30,0xbf7a7302,0x3e541501,0xbf6ed89e,0x3eb8442a,0xbf5d2d53,0x3f00e7e4,
0xbf7b14be,0xbe47c5c2,0xbf7ffb11,0xbc490e90,0xbf7c3b28,0x3e2f10a2,0xbf6ff573,0x3eb263ef,0xbf5b941a,0x3f039c3d,0xbf3fc767,0x3f299415,0xbf1d7fd1,0x3f49d112,0xbeebcbbb,0x3f633c5a,
0xbf61c598,0xbef15aea,0xbf7294f8,0xbea395c5,0xbf7cbfc9,0xbe22abb6,0xbf7ffec4,0x3bc90f88,0xbf7c3b28,0x3e2f10a2,0xbf718f57,0x3ea986c4,0xbf604621,0x3ef6e0cb,0xbf48d8b3,0x3f1ebc12,
0xbf7ec46d,0xbdc8bd36,0xbf7eea9d,0x3dbc3ac3,0xbf75dec6,0x3e8e9a22,0xbf63f473,0x3ee900b7,0xbf49d112,0x3f1d7fd1,0xbf286605,0x3f40d0da,0xbf00e7e4,0x3f5d2d53,0xbea986c4,0x3f718f57,
0x3f800000,0x0,0x3f800000,0x0,0x3f800000,0x0,0x3f800000,0x0,0x3f800000,0x0,0x3f800000,0x0,0x3f800000,0x0,0x3f800000,0x0,
0x3f54db31,0xbf0e39da,0x3f514d3d,0xbf13682a,0x3f4d9f02,0xbf187fc0,0x3f49d112,0xbf1d7fd1,0x3f45e403,0xbf226799,0x3f41d870,0xbf273656,0x3f3daef9,0xbf2beb4a,0x3f396842,0xbf3085bb,
0x3f7d3aac,0xbe164083,0x3f7cfe73,0xbe1c76de,0x3f7cbfc9,0xbe22abb6,0x3f7c7eb0,0xbe28defc,0x3f7c3b28,0xbe2f10a2,0x3f7bf531,0xbe354098,0x3f7baccd,0xbe3b6ecf,0x3f7b61fc,0xbe419b37,
0x3f3daef9,0xbf2beb4a,0x3f385216,0xbf31a81d,0x3f32c8c9,0xbf373a23,0x3f2d1469,0xbf3ca003,0x3f273656,0xbf41d870,0x3f212ff9,0xbf46e22a,0x3f1b02c6,0xbf4bbbf8,0x3f14b039,0xbf5064af,
0x3f74fa0b,0xbe94a031,0x3f740bdd,0xbe9aa086,0x3f731447,0xbea09ae5,0x3f721352,0xbea68f12,0x3f710908,0xbeac7cd4,0x3f6ff573,0xbeb263ef,0x3f6ed89e,0xbeb8442a,0x3f6db293,0xbebe1d4a,
0x3f226799,0xbf45e403,0x3f1b02c6,0xbf4bbbf8,0x3f13682a,0xbf514d3d,0x3f0b9a6b,0xbf5695e5,0x3f039c3d,0xbf5b941a,0x3ef6e0cb,0xbf604621,0x3ee63375,0xbf64aa59,0x3ed53641,0xbf68bf3c,
0x3f676bd8,0xbedae880,0x3f655e0b,0xbee363fa,0x3f633c5a,0xbeebcbbb,0x3f6106f2,0xbef41f07,0x3f5ebe05,0xbefc5d27,0x3f5c61c7,0xbf0242b1,0x3f59f26a,0xbf064b82,0x3f577026,0xbf0a48ad,
0x3f039c3d,0xbf5b941a,0x3ef41f07,0xbf6106f2,0x3ee0924f,0xbf660f88,0x3ecc9b8b,0xbf6aab7b,0x3eb8442a,0xbf6ed89e,0x3ea395c5,0xbf7294f8,0x3e8e9a22,0xbf75dec6,0x3e72b651,0xbf78b47b,
0x3ec3ef15,0xbf6c835e,0x3eac7cd4,0xbf710908,0x3e94a031,0xbf74fa0b,0x3e78cfcc,0xbf7853f8,0x3e47c5c2,0xbf7b14be,0x3e164083,0xbf7d3aac,0x3dc8bd36,0xbf7ec46d,0x3d48fb30,0xbf7fb10f,
0xbe47c5c2,0xbf7b14be,0xbe888e93,0xbf76ba07,0xbeac7cd4,0xbf710908,0xbecf7bca,0xbf6a09a7,0xbef15aea,0xbf61c598,0xbf08f59b,0xbf584853,0xbf187fc0,0xbf4d9f02,0xbf273656,0xbf41d870,
0x3e78cfcc,0xbf7853f8,0x3e419b37,0xbf7b61fc,0x3e09cf86,0xbf7dabcc,0x3da3308c,0xbf7f2f9d,0x3cc90ab0,0xbf7fec43,0xbcfb49ba,0xbf7fe129,0xbdafb680,0xbf7f0e58,0xbe1008b7,0xbf7d7474,
0xbeac7cd4,0xbf710908,0xbed25a09,0xbf696591,0xbef6e0cb,0xbf604621,0xbf0cead0,0xbf55b993,0xbf1d7fd1,0xbf49d112,0xbf2d1469,0xbf3ca003,0xbf3b8f3b,0xbf2e3bde,0xbf48d8b3,0xbf1ebc12,
0x3dc8bd36,0xbf7ec46d,0x3d16c32c,0xbf7fd397,0xbcc90ab0,0xbf7fec43,0xbdafb680,0xbf7f0e58,0xbe164083,0xbf7d3aac,0xbe541501,0xbf7a7302,0xbe888e93,0xbf76ba07,0xbea68f12,0xbf721352,
0xbef15aea,0xbf61c598,0xbf0b9a6b,0xbf5695e5,0xbf1d7fd1,0xbf49d112,0xbf2e3bde,0xbf3b8f3b,0xbf3daef9,0xbf2beb4a,0xbf4bbbf8,0xbf1b02c6,0xbf584853,0xbf08f59b,0xbf633c5a,0xbeebcbbb,
0xbd48fb30,0xbf7fb10f,0xbdee3876,0xbf7e4323,0xbe3b6ecf,0xbf7baccd,0xbe7ee6e1,0xbf77f110,0xbea09ae5,0xbf731447,0xbec1071e,0xbf6d1c1d,0xbee0924f,0xbf660f88,0xbeff17b2,0xbf5df6be,
0xbf187fc0,0xbf4d9f02,0xbf2ac082,0xbf3ebc1b,0xbf3b8f3b,0xbf2e3bde,0xbf4ac77f,0xbf1c420c,0xbf584853,0xbf08f59b,0xbf63f473,0xbee900b7,0xbf6db293,0xbebe1d4a,0xbf756d97,0xbe919ddd,
0xbf3504f3,0xbf3504f3,0xbf45e403,0xbf226799,0xbf54db31,0xbf0e39da,0xbf61c598,0xbef15aea,0xbf6c835e,0xbec3ef15,0xbf74fa0b,0xbe94a031,0xbf7b14be,0xbe47c5c2,0xbf7ec46d,0xbdc8bd36,
0xbf7b14be,0xbe47c5c2,0xbf7f4e6d,0xbd96a905,0xbf7fb10f,0x3d48fb30,0xbf7c3b28,0x3e2f10a2,0xbf74fa0b,0x3e94a031,0xbf6a09a7,0x3ecf7bca,0xbf5b941a,0x3f039c3d,0xbf49d112,0x3f1d7fd1,
0xbf4d9f02,0xbf187fc0,0xbf5c61c7,0xbf0242b1,0xbf68bf3c,0xbed53641,0xbf7294f8,0xbea395c5,0xbf79c79d,0xbe605c13,0xbf7e4323,0xbdee3876,0xbf7ffb11,0xbc490e90,0xbf7eea9d,0x3dbc3ac3,
0xbf7fb10f,0xbd48fb30,0xbf7f2f9d,0x3da3308c,0xbf7a7302,0x3e541501,0xbf718f57,0x3ea986c4,0xbf64aa59,0x3ee63375,0xbf53fac3,0x3f0f8784,0xbf3fc767,0x3f299415,0xbf286605,0x3f40d0da,
0xbf61c598,0xbef15aea,0xbf6db293,0xbebe1d4a,0xbf76ba07,0xbe888e93,0xbf7cbfc9,0xbe22abb6,0xbf7fb10f,0xbd48fb30,0xbf7f84ab,0x3d7b2b74,0xbf7c3b28,0x3e2f10a2,0xbf75dec6,0x3e8e9a22,
0xbf7ec46d,0x3dc8bd36,0xbf791298,0x3e6c9a7f,0xbf6ed89e,0x3eb8442a,0xbf604621,0x3ef6e0cb,0xbf4d9f02,0x3f187fc0,0xbf373a23,0x3f32c8c9,0xbf1d7fd1,0x3f49d112,0xbf00e7e4,0x3f5d2d53,
0xbf710908,0xbeac7cd4,0xbf796e4e,0xbe667c66,0xbf7e70b0,0xbde1bc2e,0xbf7ffec4,0x3bc90f88,0xbf7e1324,0x3dfab273,0xbf78b47b,0x3e72b651,0xbf6ff573,0x3eb263ef,0xbf63f473,0x3ee900b7,
0xbf7853f8,0x3e78cfcc,0xbf6d1c1d,0x3ec1071e,0xbf5d2d53,0x3f00e7e4,0xbf48d8b3,0x3f1ebc12,0xbf3085bb,0x3f396842,0xbf14b039,0x3f5064af,0xbeebcbbb,0x3f633c5a,0xbea986c4,0x3f718f57,
0xbf6c835e,0x3ec3ef15,0xbf5b941a,0x3f039c3d,0xbf45e403,0x3f226799,0xbf2beb4a,0x3f3daef9,0xbf0e39da,0x3f54db31,0xbedae880,0x3f676bd8,0xbe94a031,0x3f74fa0b,0xbe164083,0x3f7d3aac,
0xbf0e39da,0x3f54db31,0xbecf7bca,0x3f6a09a7,0xbe78cfcc,0x3f7853f8,0xbd96a905,0x3f7f4e6d,0x3dc8bd36,0x3f7ec46d,0x3e888e93,0x3f76ba07,0x3edae880,0x3f676bd8,0x3f13682a,0x3f514d3d,
0xbf5b941a,0x3f039c3d,0xbf44e3f5,0x3f239da9,0xbf299415,0x3f3fc767,0xbf0a48ad,0x3f577026,0xbecf7bca,0x3f6a09a7,0xbe8586ce,0x3f772417,0xbde1bc2e,0x3f7e70b0,0x3d2fe007,0x3f7fc38f,
0xbedae880,0x3f676bd8,0xbe8586ce,0x3f772417,0xbdafb680,0x3f7f0e58,0x3dbc3ac3,0x3f7eea9d,0x3e888e93,0x3f76ba07,0x3eddbe79,0x3f66becc,0x3f15f6d9,0x3f4f7a1f,0x3f385216,0x3f31a81d,
0xbf45e403,0x3f226799,0xbf299415,0x3f3fc767,0xbf08f59b,0x3f584853,0xbec9b953,0x3f6b4b0c,0xbe78cfcc,0x3f7853f8,0xbdafb680,0x3f7f0e58,0x3d96a905,0x3f7f4e6d,0x3e6c9a7f,0x3f791298,
0xbe94a031,0x3f74fa0b,0xbde1bc2e,0x3f7e70b0,0x3d96a905,0x3f7f4e6d,0x3e827dc0,0x3f778bc5,0x3edae880,0x3f676bd8,0x3f15f6d9,0x3f4f7a1f,0x3f396842,0x3f3085bb,0x3f5695e5,0x3f0b9a6b,
0xbf2beb4a,0x3f3daef9,0xbf0a48ad,0x3f577026,0xbec9b953,0x3f6b4b0c,0xbe72b651,0x3f78b47b,0xbd96a905,0x3f7f4e6d,0x3dbc3ac3,0x3f7eea9d,0x3e827dc0,0x3f778bc5,0x3ed25a09,0x3f696591,
0xbe164083,0x3f7d3aac,0x3d2fe007,0x3f7fc38f,0x3e6c9a7f,0x3f791298,0x3ed25a09,0x3f696591,0x3f13682a,0x3f514d3d,0x3f385216,0x3f31a81d,0x3f5695e5,0x3f0b9a6b,0x3f6d1c1d,0x3ec1071e,
0x3e00,0x3e00,0x3e00,0x3e00,0x3e00,0x3e00,0x3e00,0x3e00,0x3e00,0x3e00,0x3e00,0x3e00,0x3e00,0x3e00,0x3e00,0x3e00,
0xbd443ded,0xbcc83dfb,0xbc493dff,0xbd153df5,0xbdb53db5,0xbdd53d8e,0xbdc63da2,0xbde23d71,0xbe000000,0xbdfbbcc8,0xbdffbc49,0xbdf5bd15,0xbdb5bdb5,0xbd8ebdd5,0xbda2bdc6,0xbd71bde2,
0xbdb53db5,0xbd443ded,0xbcc83dfb,0xbd8e3dd5,0xbe000000,0xbdedbd44,0xbdfbbcc8,0xbdd5bd8e,0xbe00,0x3d44bded,0x3cc8bdfb,0x3d8ebdd5,0x3e000000,0x3ded3d44,0x3dfb3cc8,0x3dd53d8e,
0xbded3d44,0xbd8e3dd5,0xbd153df5,0xbdc63da2,0xbdb5bdb5,0xbcc8bdfb,0xbd71bde2,0x3c49bdff,0x3e000000,0x3dd53d8e,0x3df53d15,0x3da23dc6,0xbdb53db5,0xbdfb3cc8,0xbde23d71,0xbdffbc49,
0xbe000000,0xbdb53db5,0xbd443ded,0xbded3d44,0xbe00,0x3db5bdb5,0x3d44bded,0x3dedbd44,0x3e00,0xbdb53db5,0xbd443ded,0xbded3d44,0xbe00,0x3db5bdb5,0x3d44bded,0x3dedbd44,
0xbdedbd44,0xbdd53d8e,0xbd713de2,0xbdff3c49,0x3db5bdb5,0x3dfb3cc8,0x3df5bd15,0x3dc63da2,0xbe000000,0xbd8ebdd5,0xbde2bd71,0xbc49bdff,0x3db53db5,0xbcc83dfb,0x3d153df5,0xbda23dc6,
0xbdb5bdb5,0xbded3d44,0xbd8e3dd5,0xbdfbbcc8,0x3e000000,0x3d443ded,0x3dd53d8e,0xbcc83dfb,0xbe00,0x3dedbd44,0x3d8ebdd5,0x3dfb3cc8,0xbe000000,0xbd44bded,0xbdd5bd8e,0x3cc8bdfb,
0xbd44bded,0xbdfb3cc8,0xbda23dc6,0xbde2bd71,0x3db53db5,0xbd8e3dd5,0x3c493dff,0xbdf53d15,0x3e000000,0x3cc83dfb,0x3dc63da2,0xbd713de2,0x3db5bdb5,0x3dd53d8e,0x3dffbc49,0x3d153df5,
0xbe00,0xbe000000,0xbdb53db5,0xbdb5bdb5,0x3e00,0xbe000000,0xbdb53db5,0xbdb5bdb5,0x3e00,0xbe000000,0xbdb53db5,0xbdb5bdb5,0x3e00,0xbe000000,0xbdb53db5,0xbdb5bdb5,
0x3d44bded,0xbdfbbcc8,0xbdc63da2,0xbd71bde2,0xbdb53db5,0xbd8ebdd5,0xbdffbc49,0x3d15bdf5,0xbe000000,0x3cc8bdfb,0xbda2bdc6,0x3de2bd71,0xbdb5bdb5,0x3dd5bd8e,0x3c49bdff,0x3df53d15,
0x3db5bdb5,0xbdedbd44,0xbdd53d8e,0xbcc8bdfb,0xbe000000,0x3d44bded,0xbd8ebdd5,0x3dfbbcc8,0xbe00,0x3ded3d44,0x3dd5bd8e,0x3cc83dfb,0x3e000000,0xbd443ded,0x3d8e3dd5,0xbdfb3cc8,
0x3dedbd44,0xbdd5bd8e,0xbde23d71,0x3c49bdff,0xbdb5bdb5,0x3dfbbcc8,0x3d15bdf5,0x3da23dc6,0x3e000000,0xbd8e3dd5,0x3d713de2,0xbdffbc49,0xbdb53db5,0xbcc8bdfb,0xbdf5bd15,0x3dc6bda2,
0x3e000000,0xbdb5bdb5,0xbded3d44,0x3d44bded,0xbe00,0x3db53db5,0x3dedbd44,0xbd443ded,0x3e00,0xbdb5bdb5,0xbded3d44,0x3d44bded,0xbe00,0x3db53db5,0x3dedbd44,0xbd443ded,
0x3ded3d44,0xbd8ebdd5,0xbdf53d15,0x3da2bdc6,0x3db5bdb5,0xbcc83dfb,0x3de23d71,0xbdff3c49,0xbe000000,0x3dd5bd8e,0xbd15bdf5,0x3dc63da2,0x3db53db5,0xbdfbbcc8,0xbd713de2,0xbc49bdff,
0x3db53db5,0xbd44bded,0xbdfb3cc8,0x3dd5bd8e,0x3e000000,0xbded3d44,0x3cc83dfb,0xbd8ebdd5,0xbe00,0x3d443ded,0x3dfbbcc8,0xbdd53d8e,0xbe000000,0x3dedbd44,0xbcc8bdfb,0x3d8e3dd5,
0x3d443ded,0xbcc8bdfb,0xbdff3c49,0x3df5bd15,0x3db53db5,0xbdd5bd8e,0xbda23dc6,0x3d71bde2,0x3e000000,0xbdfb3cc8,0x3c493dff,0xbd15bdf5,0x3db5bdb5,0xbd8e3dd5,0x3dc63da2,0xbde2bd71,
0x3e00,0xbe00,0xbe000000,0x3e000000,0x3e00,0xbe00,0xbe000000,0x3e000000,0x3e00,0xbe00,0xbe000000,0x3e000000,0x3e00,0xbe00,0xbe000000,0x3e000000,
0xbd443ded,0x3cc8bdfb,0xbdffbc49,0x3df53d15,0xbdb53db5,0x3dd5bd8e,0xbda2bdc6,0x3d713de2,0xbe000000,0x3dfb3cc8,0x3c49bdff,0xbd153df5,0xbdb5bdb5,0x3d8e3dd5,0x3dc6bda2,0xbde23d71,
0xbdb53db5,0x3d44bded,0xbdfbbcc8,0x3dd53d8e,0xbe000000,0x3ded3d44,0x3cc8bdfb,0xbd8e3dd5,0xbe00,0xbd443ded,0x3dfb3cc8,0xbdd5bd8e,0x3e000000,0xbdedbd44,0xbcc83dfb,0x3d8ebdd5,
0xbded3d44,0x3d8ebdd5,0xbdf5bd15,0x3da23dc6,0xbdb5bdb5,0x3cc83dfb,0x3de2bd71,0xbdffbc49,0x3e000000,0xbdd5bd8e,0xbd153df5,0x3dc6bda2,0xbdb53db5,0x3dfbbcc8,0xbd71bde2,0xbc493dff,
0xbe000000,0x3db5bdb5,0xbdedbd44,0x3d443ded,0xbe00,0xbdb53db5,0x3ded3d44,0xbd44bded,0x3e00,0x3db5bdb5,0xbdedbd44,0x3d443ded,0xbe00,0xbdb53db5,0x3ded3d44,0xbd44bded,
0xbdedbd44,0x3dd5bd8e,0xbde2bd71,0x3c493dff,0x3db5bdb5,0xbdfbbcc8,0x3d153df5,0x3da2bdc6,0xbe000000,0x3d8e3dd5,0x3d71bde2,0xbdff3c49,0x3db53db5,0x3cc8bdfb,0xbdf53d15,0x3dc63da2,
0xbdb5bdb5,0x3dedbd44,0xbdd5bd8e,0xbcc83dfb,0x3e000000,0xbd44bded,0xbd8e3dd5,0x3dfb3cc8,0xbe00,0xbded3d44,0x3dd53d8e,0x3cc8bdfb,0xbe000000,0x3d443ded,0x3d8ebdd5,0xbdfbbcc8,
0xbd44bded,0x3dfbbcc8,0xbdc6bda2,0xbd713de2,0x3db53db5,0x3d8ebdd5,0xbdff3c49,0x3d153df5,0x3e000000,0xbcc8bdfb,0xbda23dc6,0x3de23d71,0x3db5bdb5,0xbdd5bd8e,0x3c493dff,0x3df5bd15,
0xbe00,0x3e000000,0xbdb5bdb5,0xbdb53db5,0x3e00,0x3e000000,0xbdb5bdb5,0xbdb53db5,0x3e00,0x3e000000,0xbdb5bdb5,0xbdb53db5,0x3e00,0x3e000000,0xbdb5bdb5,0xbdb53db5,
0x3d44bded,0x3dfb3cc8,0xbda2bdc6,0xbde23d71,0xbdb53db5,0x3d8e3dd5,0x3c49bdff,0xbdf5bd15,0xbe000000,0xbcc83dfb,0x3dc6bda2,0xbd71bde2,0xbdb5bdb5,0xbdd53d8e,0x3dff3c49,0x3d15bdf5,
0x3db5bdb5,0x3ded3d44,0xbd8ebdd5,0xbdfb3cc8,0xbe000000,0xbd443ded,0x3dd5bd8e,0xbcc8bdfb,0xbe00,0xbdedbd44,0x3d8e3dd5,0x3dfbbcc8,0x3e000000,0x3d44bded,0xbdd53d8e,0x3cc83dfb,
0x3dedbd44,0x3dd53d8e,0xbd71bde2,0xbdffbc49,0xbdb5bdb5,0xbdfb3cc8,0x3df53d15,0x3dc6bda2,0x3e000000,0x3d8ebdd5,0xbde23d71,0xbc493dff,0xbdb53db5,0x3cc83dfb,0x3d15bdf5,0xbda2bdc6,
0x3e000000,0x3db53db5,0xbd44bded,0xbdedbd44,0xbe00,0xbdb5bdb5,0x3d443ded,0x3ded3d44,0x3e00,0x3db53db5,0xbd44bded,0xbdedbd44,0xbe00,0xbdb5bdb5,0x3d443ded,0x3ded3d44,
0x3ded3d44,0x3d8e3dd5,0xbd15bdf5,0xbdc6bda2,0x3db5bdb5,0x3cc8bdfb,0xbd713de2,0x3c493dff,0xbe000000,0xbdd53d8e,0x3df5bd15,0x3da2bdc6,0x3db53db5,0x3dfb3cc8,0xbde2bd71,0xbdff3c49,
0x3db53db5,0x3d443ded,0xbcc8bdfb,0xbd8ebdd5,0x3e000000,0x3dedbd44,0xbdfb3cc8,0xbdd53d8e,0xbe00,0xbd44bded,0x3cc83dfb,0x3d8e3dd5,0xbe000000,0xbded3d44,0x3dfbbcc8,0x3dd5bd8e,
0x3d443ded,0x3cc83dfb,0xbc49bdff,0xbd15bdf5,0x3db53db5,0x3dd53d8e,0xbdc6bda2,0xbde2bd71,0x3e000000,0x3dfbbcc8,0xbdff3c49,0xbdf53d15,0x3db5bdb5,0x3d8ebdd5,0xbda23dc6,0xbd713de2,
0x3d803d80,0x3e00,0x3e00,0x3e00,0x3e00,0x3e00,0x3e00,0x3e00,0x3e00,0x3e00,0x3e00,0x3e00,0x3e00,0x3e00,0x3e00,0x3e00,
0xbd803d80,0x3cc8bdfb,0x3c49bdff,0x3d15bdf5,0xbded3d44,0x3dd5bd8e,0x3dc6bda2,0x3de2bd71,0xbdedbd44,0x3dfb3cc8,0x3dff3c49,0x3df53d15,0xbd44bded,0x3d8e3dd5,0x3da23dc6,0x3d713de2,
0x3d803d80,0xbd443ded,0xbcc83dfb,0xbd8e3dd5,0xbdb5bdb5,0xbdedbd44,0xbdfbbcc8,0xbdd5bd8e,0x3db5bdb5,0x3d44bded,0x3cc8bdfb,0x3d8ebdd5,0x3db53db5,0x3ded3d44,0x3dfb3cc8,0x3dd53d8e,
0xbd803d80,0x3d8ebdd5,0x3d15bdf5,0x3dc6bda2,0x3d44bded,0x3cc83dfb,0x3d713de2,0xbc493dff,0x3d443ded,0xbdd5bd8e,0xbdf5bd15,0xbda2bdc6,0xbdedbd44,0x3dfbbcc8,0x3de2bd71,0x3dff3c49,
0x3d803d80,0xbdb53db5,0xbd443ded,0xbded3d44,0x3e000000,0x3db5bdb5,0x3d44bded,0x3dedbd44,0xbe000000,0xbdb53db5,0xbd443ded,0xbded3d44,0x3e000000,0x3db5bdb5,0x3d44bded,0x3dedbd44,
0xbd803d80,0x3dd5bd8e,0x3d71bde2,0x3dffbc49,0x3d443ded,0xbdfbbcc8,0xbdf53d15,0xbdc6bda2,0x3d44bded,0x3d8e3dd5,0x3de23d71,0x3c493dff,0xbded3d44,0x3cc8bdfb,0xbd15bdf5,0x3da2bdc6,
0x3d803d80,0xbded3d44,0xbd8e3dd5,0xbdfbbcc8,0xbdb53db5,0x3d443ded,0x3dd53d8e,0xbcc83dfb,0x3db53db5,0x3dedbd44,0x3d8ebdd5,0x3dfb3cc8,0x3db5bdb5,0xbd44bded,0xbdd5bd8e,0x3cc8bdfb,
0xbd803d80,0x3dfbbcc8,0x3da2bdc6,0x3de23d71,0xbdedbd44,0x3d8ebdd5,0xbc49bdff,0x3df5bd15,0xbded3d44,0xbcc8bdfb,0xbdc6bda2,0x3d71bde2,0xbd443ded,0xbdd5bd8e,0xbdff3c49,0xbd15bdf5,
0x3d803d80,0xbe000000,0xbdb53db5,0xbdb5bdb5,0xbe00,0xbe000000,0xbdb53db5,0xbdb5bdb5,0xbe00,0xbe000000,0xbdb53db5,0xbdb5bdb5,0xbe00,0xbe000000,0xbdb53db5,0xbdb5bdb5,
0xbd803d80,0x3dfb3cc8,0x3dc6bda2,0x3d713de2,0x3dedbd44,0x3d8e3dd5,0x3dff3c49,0xbd153df5,0x3ded3d44,0xbcc83dfb,0x3da23dc6,0xbde23d71,0x3d443ded,0xbdd53d8e,0xbc493dff,0xbdf5bd15,
0x3d803d80,0xbdedbd44,0xbdd53d8e,0xbcc8bdfb,0x3db53db5,0x3d44bded,0xbd8ebdd5,0x3dfbbcc8,0xbdb53db5,0x3ded3d44,0x3dd5bd8e,0x3cc83dfb,0xbdb5bdb5,0xbd443ded,0x3d8e3dd5,0xbdfb3cc8,
0xbd803d80,0x3dd53d8e,0x3de2bd71,0xbc493dff,0xbd443ded,0xbdfb3cc8,0xbd153df5,0xbda2bdc6,0xbd44bded,0x3d8ebdd5,0xbd71bde2,0x3dff3c49,0x3ded3d44,0x3cc83dfb,0x3df53d15,0xbdc63da2,
0x3d803d80,0xbdb5bdb5,0xbded3d44,0x3d44bded,0xbe000000,0x3db53db5,0x3dedbd44,0xbd443ded,0x3e000000,0xbdb5bdb5,0xbded3d44,0x3d44bded,0xbe000000,0x3db53db5,0x3dedbd44,0xbd443ded,
0xbd803d80,0x3d8e3dd5,0x3df5bd15,0xbda23dc6,0xbd44bded,0x3cc8bdfb,0xbde2bd71,0x3dffbc49,0xbd443ded,0xbdd53d8e,0x3d153df5,0xbdc6bda2,0x3dedbd44,0x3dfb3cc8,0x3d71bde2,0x3c493dff,
0x3d803d80,0xbd44bded,0xbdfb3cc8,0x3dd5bd8e,0x3db5bdb5,0xbded3d44,0x3cc83dfb,0xbd8ebdd5,0xbdb5bdb5,0x3d443ded,0x3dfbbcc8,0xbdd53d8e,0xbdb53db5,0x3dedbd44,0xbcc8bdfb,0x3d8e3dd5,
0xbd803d80,0x3cc83dfb,0x3dffbc49,0xbdf53d15,0x3ded3d44,0x3dd53d8e,0x3da2bdc6,0xbd713de2,0x3dedbd44,0x3dfbbcc8,0xbc49bdff,0x3d153df5,0x3d44bded,0x3d8ebdd5,0xbdc6bda2,0x3de23d71,
0x3d803d80,0xbe00,0xbe000000,0x3e000000,0x3e00,0xbe00,0xbe000000,0x3e000000,0x3e00,0xbe00,0xbe000000,0x3e000000,0x3e00,0xbe00,0xbe000000,0x3e000000,
0xbd803d80,0xbcc83dfb,0x3dff3c49,0xbdf5bd15,0xbded3d44,0xbdd53d8e,0x3da23dc6,0xbd71bde2,0xbdedbd44,0xbdfbbcc8,0xbc493dff,0x3d15bdf5,0xbd44bded,0xbd8ebdd5,0xbdc63da2,0x3de2bd71,
0x3d803d80,0x3d44bded,0xbdfbbcc8,0x3dd53d8e,0xbdb5bdb5,0x3ded3d44,0x3cc8bdfb,0xbd8e3dd5,0x3db5bdb5,0xbd443ded,0x3dfb3cc8,0xbdd5bd8e,0x3db53db5,0xbdedbd44,0xbcc83dfb,0x3d8ebdd5,
0xbd803d80,0xbd8e3dd5,0x3df53d15,0xbda2bdc6,0x3d44bded,0xbcc8bdfb,0xbde23d71,0x3dff3c49,0x3d443ded,0x3dd53d8e,0x3d15bdf5,0xbdc63da2,0xbdedbd44,0xbdfb3cc8,0x3d713de2,0x3c49bdff,
0x3d803d80,0x3db5bdb5,0xbdedbd44,0x3d443ded,0x3e000000,0xbdb53db5,0x3ded3d44,0xbd44bded,0xbe000000,0x3db5bdb5,0xbdedbd44,0x3d443ded,0x3e000000,0xbdb53db5,0x3ded3d44,0xbd44bded,
0xbd803d80,0xbdd53d8e,0x3de23d71,0xbc49bdff,0x3d443ded,0x3dfb3cc8,0xbd15bdf5,0xbda23dc6,0x3d44bded,0xbd8ebdd5,0xbd713de2,0x3dffbc49,0xbded3d44,0xbcc83dfb,0x3df5bd15,0xbdc6bda2,
0x3d803d80,0x3dedbd44,0xbdd5bd8e,0xbcc83dfb,0xbdb53db5,0xbd44bded,0xbd8e3dd5,0x3dfb3cc8,0x3db53db5,0xbded3d44,0x3dd53d8e,0x3cc8bdfb,0x3db5bdb5,0x3d443ded,0x3d8ebdd5,0xbdfbbcc8,
0xbd803d80,0xbdfb3cc8,0x3dc63da2,0x3d71bde2,0xbdedbd44,0xbd8e3dd5,0x3dffbc49,0xbd15bdf5,0xbded3d44,0x3cc83dfb,0x3da2bdc6,0xbde2bd71,0xbd443ded,0x3dd53d8e,0xbc49bdff,0xbdf53d15,
0x3d803d80,0x3e000000,0xbdb5bdb5,0xbdb53db5,0xbe00,0x3e000000,0xbdb5bdb5,0xbdb53db5,0xbe00,0x3e000000,0xbdb5bdb5,0xbdb53db5,0xbe00,0x3e000000,0xbdb5bdb5,0xbdb53db5,
0xbd803d80,0xbdfbbcc8,0x3da23dc6,0x3de2bd71,0x3dedbd44,0xbd8ebdd5,0xbc493dff,0x3df53d15,0x3ded3d44,0x3cc8bdfb,0xbdc63da2,0x3d713de2,0x3d443ded,0x3dd5bd8e,0xbdffbc49,0xbd153df5,
0x3d803d80,0x3ded3d44,0xbd8ebdd5,0xbdfb3cc8,0x3db53db5,0xbd443ded,0x3dd5bd8e,0xbcc8bdfb,0xbdb53db5,0xbdedbd44,0x3d8e3dd5,0x3dfbbcc8,0xbdb5bdb5,0x3d44bded,0xbdd53d8e,0x3cc83dfb,
0xbd803d80,0xbdd5bd8e,0x3d713de2,0x3dff3c49,0xbd443ded,0x3dfbbcc8,0xbdf5bd15,0xbdc63da2,0xbd44bded,0xbd8e3dd5,0x3de2bd71,0x3c49bdff,0x3ded3d44,0xbcc8bdfb,0xbd153df5,0x3da23dc6,
0x3d803d80,0x3db53db5,0xbd44bded,0xbdedbd44,0xbe000000,0xbdb5bdb5,0x3d443ded,0x3ded3d44,0x3e000000,0x3db53db5,0xbd44bded,0xbdedbd44,0xbe000000,0xbdb5bdb5,0x3d443ded,0x3ded3d44,
0xbd803d80,0xbd8ebdd5,0x3d153df5,0x3dc63da2,0xbd44bded,0xbcc83dfb,0x3d71bde2,0xbc49bdff,0xbd443ded,0x3dd5bd8e,0xbdf53d15,0xbda23dc6,0x3dedbd44,0xbdfbbcc8,0x3de23d71,0x3dffbc49,
0x3d803d80,0x3d443ded,0xbcc8bdfb,0xbd8ebdd5,0x3db5bdb5,0x3dedbd44,0xbdfb3cc8,0xbdd53d8e,0xbdb5bdb5,0xbd44bded,0x3cc83dfb,0x3d8e3dd5,0xbdb53db5,0xbded3d44,0x3dfbbcc8,0x3dd5bd8e,
0xbd803d80,0xbcc8bdfb,0x3c493dff,0x3d153df5,0x3ded3d44,0xbdd5bd8e,0x3dc63da2,0x3de23d71,0x3dedbd44,0xbdfb3cc8,0x3dffbc49,0x3df5bd15,0x3d44bded,0xbd8e3dd5,0x3da2bdc6,0x3d71bde2,
0xbc493dff,0xbbc93e00,0xbb493e00,0xbc173dff,0xbcc83dfb,0xbcf93df8,0xbce03dfa,0xbd093df7,0xbd443ded,0xbd5b3de7,0xbd4f3dea,0xbd663de5,0xbd8e3dd5,0xbd983dce,0xbd933dd1,0xbd9d3dca,
0xbd713de2,0xbcf93df8,0xbc7b3dfe,0xbd383def,0xbdd53d8e,0xbdf13d2c,0xbde53d66,0xbdfa3ce0,0xbdedbd44,0xbdcebd98,0xbddfbd7c,0xbdb9bdb1,0xbcc8bdfb,0x3bc9be00,0xbc17bdff,0x3cafbdfc,
0xbdc63da2,0xbd5b3de7,0xbce03dfa,0xbd9d3dca,0xbdfbbcc8,0xbdcebd98,0xbdeabd4f,0xbda7bdc2,0x3d44bded,0x3dbebdac,0x3d93bdd1,0x3ddfbd7c,0x3dd53d8e,0x3d843ddc,0x3db13db9,0x3d213df3,
0xbdf53d15,0xbd983dce,0xbd213df3,0xbdd13d93,0xbd8ebdd5,0x3bc9be00,0xbd09bdf7,0x3d38bdef,0x3ded3d44,0x3d843ddc,0x3dc23da7,0x3ce03dfa,0xbdfb3cc8,0xbde7bd5b,0xbdfebc7b,0xbdb9bdb1,
0xbdffbc49,0xbdbe3dac,0xbd4f3dea,0xbdf33d21,0x3cc8bdfb,0x3ddcbd84,0x3d93bdd1,0x3dfebc7b,0xbd443ded,0xbdf13d2c,0xbdb93db1,0xbdffbc17,0x3d8ebdd5,0x3dfdbc96,0x3dd8bd89,0x3df73d09,
0xbde2bd71,0xbddc3d84,0xbd7c3ddf,0xbe003b49,0x3dd5bd8e,0x3de73d5b,0x3dffbc17,0x3d933dd1,0xbdedbd44,0xbc96bdfd,0xbd9dbdca,0x3d38bdef,0x3cc83dfb,0xbdbe3dac,0xbd213df3,0xbdfa3ce0,
0xbda2bdc6,0xbdf13d2c,0xbd933dd1,0xbdf7bd09,0x3dfb3cc8,0x3c963dfd,0x3db13db9,0xbd663de5,0x3d44bded,0x3e003bc9,0x3dd8bd89,0x3dca3d9d,0xbdd5bd8e,0x3cf9bdf8,0xbd38bdef,0x3dc2bda7,
0xbd15bdf5,0xbdfd3c96,0xbda73dc2,0xbdd8bd89,0x3d8e3dd5,0xbdbe3dac,0xbc7b3dfe,0xbe003b49,0x3ded3d44,0xbcf93df8,0x3d663de5,0xbdd13d93,0x3dfbbcc8,0x3d2c3df1,0x3ddf3d7c,0xbd383def,
0x3c49bdff,0xbe00bbc9,0xbdb93db1,0xbda7bdc2,0xbcc83dfb,0xbdf8bcf9,0xbdd83d89,0xbd7cbddf,0xbd443ded,0xbde7bd5b,0xbdef3d38,0xbd21bdf3,0xbd8e3dd5,0xbdcebd98,0xbdfc3caf,0xbc7bbdfe,
0x3d71bde2,0xbdf8bcf9,0xbdca3d9d,0xbd4fbdea,0xbdd53d8e,0xbd2cbdf1,0xbdf3bd21,0x3d89bdd8,0xbdedbd44,0x3d98bdce,0xbd09bdf7,0x3e00bb49,0xbcc8bdfb,0x3e003bc9,0x3da7bdc2,0x3d933dd1,
0x3dc6bda2,0xbde7bd5b,0xbdd83d89,0xbc7bbdfe,0xbdfbbcc8,0x3d98bdce,0xbd38bdef,0x3dff3c17,0x3d44bded,0x3dac3dbe,0x3dfcbcaf,0xbd093df7,0x3dd53d8e,0xbddc3d84,0xbb493e00,0xbde5bd66,
0x3df5bd15,0xbdcebd98,0xbde53d66,0x3cafbdfc,0xbd8ebdd5,0x3e003bc9,0x3d7cbddf,0x3d4f3dea,0x3ded3d44,0xbddc3d84,0x3c173dff,0xbdd8bd89,0xbdfb3cc8,0x3d5bbde7,0xbd9dbdca,0x3e00bb49,
0x3dff3c49,0xbdacbdbe,0xbdef3d38,0x3d66bde5,0x3cc8bdfb,0x3d843ddc,0x3dfcbcaf,0xbd9d3dca,0xbd443ded,0xbd2cbdf1,0xbe00bb49,0x3dc2bda7,0x3d8ebdd5,0x3c963dfd,0x3dfa3ce0,0xbddf3d7c,
0x3de23d71,0xbd84bddc,0xbdf73d09,0x3db1bdb9,0x3dd5bd8e,0xbd5b3de7,0x3dc23da7,0xbdfcbcaf,0xbdedbd44,0x3dfdbc96,0x3c7bbdfe,0x3d4f3dea,0x3cc83dfb,0xbdacbdbe,0xbde53d66,0x3d89bdd8,
0x3da23dc6,0xbd2cbdf1,0xbdfc3caf,0x3ddfbd7c,0x3dfb3cc8,0xbdfd3c96,0xbb493e00,0xbd21bdf3,0x3d44bded,0xbbc93e00,0x3dfa3ce0,0xbdfe3c7b,0xbdd5bd8e,0x3df83cf9,0x3d4fbdea,0xbc173dff,
0x3d153df5,0xbc96bdfd,0xbdff3c17,0x3dfabce0,0x3d8e3dd5,0xbdacbdbe,0xbdca3d9d,0x3db1bdb9,0x3ded3d44,0xbdf8bcf9,0xbd213df3,0x3cafbdfc,0x3dfbbcc8,0xbdf13d2c,0x3d093df7,0xbd4fbdea,
0xbc493dff,0x3bc9be00,0xbe00bb49,0x3dff3c17,0xbcc83dfb,0x3cf9bdf8,0xbdfabce0,0x3df73d09,0xbd443ded,0x3d5bbde7,0xbdeabd4f,0x3de53d66,0xbd8e3dd5,0x3d98bdce,0xbdd1bd93,0x3dca3d9d,
0xbd713de2,0x3cf9bdf8,0xbdfebc7b,0x3def3d38,0xbdd53d8e,0x3df1bd2c,0xbd66bde5,0x3ce03dfa,0xbdedbd44,0x3dce3d98,0x3d7cbddf,0xbdb13db9,0xbcc8bdfb,0xbbc93e00,0x3dffbc17,0xbdfcbcaf,
0xbdc63da2,0x3d5bbde7,0xbdfabce0,0x3dca3d9d,0xbdfbbcc8,0x3dce3d98,0x3d4fbdea,0xbdc23da7,0x3d44bded,0xbdbe3dac,0x3dd13d93,0xbd7cbddf,0x3dd53d8e,0xbd84bddc,0xbdb93db1,0x3df3bd21,
0xbdf53d15,0x3d98bdce,0xbdf3bd21,0x3d933dd1,0xbd8ebdd5,0xbbc93e00,0x3df7bd09,0xbdefbd38,0x3ded3d44,0xbd84bddc,0xbda73dc2,0x3dfabce0,0xbdfb3cc8,0x3de73d5b,0x3c7bbdfe,0xbdb13db9,
0xbdffbc49,0x3dbebdac,0xbdeabd4f,0x3d213df3,0x3cc8bdfb,0xbddc3d84,0x3dd13d93,0xbc7bbdfe,0xbd443ded,0x3df1bd2c,0xbdb1bdb9,0xbc173dff,0x3d8ebdd5,0xbdfd3c96,0x3d893dd8,0x3d09bdf7,
0xbde2bd71,0x3ddcbd84,0xbddfbd7c,0x3b493e00,0x3dd5bd8e,0xbde7bd5b,0x3c173dff,0x3dd1bd93,0xbdedbd44,0x3c963dfd,0x3dcabd9d,0xbdefbd38,0x3cc83dfb,0x3dbebdac,0xbdf3bd21,0x3ce03dfa,
0xbda2bdc6,0x3df1bd2c,0xbdd1bd93,0xbd093df7,0x3dfb3cc8,0xbc96bdfd,0xbdb93db1,0x3de53d66,0x3d44bded,0xbe00bbc9,0x3d893dd8,0x3d9dbdca,0xbdd5bd8e,0xbcf93df8,0x3defbd38,0xbda7bdc2,
0xbd15bdf5,0x3dfdbc96,0xbdc2bda7,0xbd893dd8,0x3d8e3dd5,0x3dbebdac,0xbdfebc7b,0x3b493e00,0x3ded3d44,0x3cf9bdf8,0xbde53d66,0x3d933dd1,0x3dfbbcc8,0xbd2cbdf1,0xbd7c3ddf,0x3def3d38,
0x3c49bdff,0x3e003bc9,0xbdb1bdb9,0xbdc23da7,0xbcc83dfb,0x3df83cf9,0xbd89bdd8,0xbddf3d7c,0xbd443ded,0x3de73d5b,0xbd38bdef,0xbdf33d21,0xbd8e3dd5,0x3dce3d98,0xbcafbdfc,0xbdfe3c7b,
0x3d71bde2,0x3df83cf9,0xbd9dbdca,0xbdea3d4f,0xbdd53d8e,0x3d2c3df1,0x3d21bdf3,0xbdd8bd89,0xbdedbd44,0xbd983dce,0x3df7bd09,0xbb49be00,0xbcc8bdfb,0xbe00bbc9,0x3dc23da7,0x3dd1bd93,
0x3dc6bda2,0x3de73d5b,0xbd89bdd8,0xbdfe3c7b,0xbdfbbcc8,0xbd983dce,0x3defbd38,0x3c17bdff,0x3d44bded,0xbdacbdbe,0x3caf3dfc,0x3df73d09,0x3dd53d8e,0x3ddcbd84,0xbe00bb49,0xbd663de5,
0x3df5bd15,0x3dce3d98,0xbd66bde5,0xbdfcbcaf,0xbd8ebdd5,0xbe00bbc9,0x3ddf3d7c,0x3deabd4f,0x3ded3d44,0x3ddcbd84,0xbdff3c17,0xbd893dd8,0xbdfb3cc8,0xbd5b3de7,0x3dcabd9d,0xbb49be00,
0x3dff3c49,0x3dac3dbe,0xbd38bdef,0xbde5bd66,0x3cc8bdfb,0xbd84bddc,0x3caf3dfc,0x3dca3d9d,0xbd443ded,0x3d2c3df1,0x3b49be00,0xbda7bdc2,0x3d8ebdd5,0xbc96bdfd,0xbce03dfa,0x3d7c3ddf,
0x3de23d71,0x3d843ddc,0xbd09bdf7,0xbdb9bdb1,0x3dd5bd8e,0x3d5bbde7,0xbda73dc2,0xbcaf3dfc,0xbdedbd44,0xbdfd3c96,0x3dfe3c7b,0x3deabd4f,0x3cc83dfb,0x3dac3dbe,0xbd66bde5,0xbdd8bd89,
0x3da23dc6,0x3d2c3df1,0xbcafbdfc,0xbd7cbddf,0x3dfb3cc8,0x3dfdbc96,0xbe00bb49,0xbdf33d21,0x3d44bded,0x3bc9be00,0xbce03dfa,0x3c7b3dfe,0xbdd5bd8e,0xbdf8bcf9,0x3dea3d4f,0x3dff3c17,
0x3d153df5,0x3c963dfd,0xbc17bdff,0xbce0bdfa,0x3d8e3dd5,0x3dac3dbe,0xbd9dbdca,0xbdb9bdb1,0x3ded3d44,0x3df83cf9,0xbdf3bd21,0xbdfcbcaf,0x3dfbbcc8,0x3df1bd2c,0xbdf73d09,0xbdea3d4f,
0xbdb53d80,0xbdbe3dac,0xbdb93db1,0xbdc23da7,0xbd153df5,0xbddc3d84,0xbdd83d89,0xbddf3d7c,0xbd713de2,0xbdf13d2c,0xbdef3d38,0xbdf33d21,0xbda23dc6,0xbdfd3c96,0xbdfc3caf,0xbdfe3c7b,
0x3db53d80,0x3ddcbd84,0x3dcabd9d,0x3deabd4f,0xbdff3c49,0x3de73d5b,0x3df33d21,0x3dd83d89,0xbda2bdc6,0x3c963dfd,0x3d093df7,0x3b493e00,0x3d15bdf5,0xbdbe3dac,0xbda73dc2,0xbdd13d93,
0xbdb53d80,0xbdf13d2c,0xbdd83d89,0xbdfe3c7b,0xbd71bde2,0xbc96bdfd,0xbd38bdef,0x3c17bdff,0x3df5bd15,0x3e003bc9,0x3dfcbcaf,0x3df73d09,0x3c493dff,0xbcf93df8,0xbb493e00,0xbd663de5,
0x3db53d80,0x3dfdbc96,0x3de5bd66,0x3dfc3caf,0x3da2bdc6,0xbdbe3dac,0xbd7c3ddf,0xbdea3d4f,0xbc493dff,0x3cf9bdf8,0xbc17bdff,0x3d89bdd8,0xbd71bde2,0x3d2c3df1,0x3d9d3dca,0x3b493e00,
0xbdb53d80,0xbe00bbc9,0xbdef3d38,0xbde5bd66,0x3df53d15,0x3df83cf9,0x3dfcbcaf,0x3dca3d9d,0xbde2bd71,0xbde7bd5b,0xbe00bb49,0xbda7bdc2,0x3dc63da2,0x3dce3d98,0x3dfa3ce0,0x3d7c3ddf,
0x3db53d80,0x3df83cf9,0x3df7bd09,0x3db93db1,0x3c493dff,0xbd2cbdf1,0xbdc2bda7,0x3cafbdfc,0x3dc6bda2,0xbd983dce,0xbc7b3dfe,0xbdea3d4f,0xbdf5bd15,0x3e003bc9,0x3de5bd66,0x3dd83d89,
0xbdb53d80,0xbde7bd5b,0xbdfc3caf,0xbd7cbddf,0xbde23d71,0xbd983dce,0xbb493e00,0xbdf33d21,0x3d153df5,0x3dac3dbe,0x3dfa3ce0,0x3c7b3dfe,0x3dffbc49,0x3ddcbd84,0x3d4fbdea,0x3dff3c17,
0x3db53d80,0x3dce3d98,0x3dffbc17,0x3ce03dfa,0xbdc6bda2,0x3e003bc9,0x3dcabd9d,0x3db93db1,0xbdffbc49,0x3ddcbd84,0x3d21bdf3,0x3dfc3caf,0xbde23d71,0x3d5bbde7,0xbd09bdf7,0x3deabd4f,
0xbdb53d80,0xbdacbdbe,0xbe00bb49,0x3c17bdff,0x3d15bdf5,0xbd84bddc,0xbdfabce0,0x3d09bdf7,0x3d71bde2,0xbd2cbdf1,0xbdeabd4f,0x3d66bde5,0x3da2bdc6,0xbc96bdfd,0xbdd1bd93,0x3d9dbdca,
0x3db53d80,0x3d843ddc,0x3dfe3c7b,0xbd383def,0x3dffbc49,0xbd5b3de7,0x3d663de5,0xbdfa3ce0,0x3da23dc6,0xbdfd3c96,0xbd7c3ddf,0xbdb9bdb1,0xbd153df5,0xbdacbdbe,0xbdff3c17,0x3cafbdfc,
0xbdb53d80,0xbd2cbdf1,0xbdfabce0,0x3d9dbdca,0x3d713de2,0x3dfdbc96,0x3d4fbdea,0x3da73dc2,0xbdf53d15,0xbbc93e00,0x3dd13d93,0xbddf3d7c,0xbc49bdff,0xbdf8bcf9,0xbdb93db1,0xbd21bdf3,
0x3db53d80,0x3c963dfd,0x3df33d21,0xbdd13d93,0xbda23dc6,0xbdacbdbe,0xbdf73d09,0x3d38bdef,0x3c49bdff,0x3df83cf9,0x3da7bdc2,0x3ce03dfa,0x3d713de2,0xbdf13d2c,0xbc7b3dfe,0xbdb9bdb1,
0xbdb53d80,0x3bc9be00,0xbdeabd4f,0x3df3bd21,0xbdf5bd15,0xbcf93df8,0x3dd13d93,0xbdfe3c7b,0x3de23d71,0x3d5bbde7,0xbdb1bdb9,0x3dff3c17,0xbdc6bda2,0xbd983dce,0x3d893dd8,0xbdf7bd09,
0x3db53d80,0xbcf93df8,0x3ddf3d7c,0xbe003b49,0xbc49bdff,0x3df1bd2c,0xbc17bdff,0x3d933dd1,0xbdc63da2,0xbdcebd98,0xbdca3d9d,0x3d38bdef,0x3df53d15,0xbbc93e00,0x3df33d21,0xbdfa3ce0,
0xbdb53d80,0x3d5bbde7,0xbdd1bd93,0x3df73d09,0x3de2bd71,0xbdcebd98,0xbdb93db1,0x3d66bde5,0xbd15bdf5,0xbdbe3dac,0x3d893dd8,0xbdcabd9d,0xbdff3c49,0x3d843ddc,0x3defbd38,0xbdc23da7,
0x3db53d80,0xbd983dce,0x3dc23da7,0xbdd8bd89,0x3dc63da2,0xbbc93e00,0x3dfe3c7b,0xbe003b49,0x3dff3c49,0x3d843ddc,0x3de5bd66,0xbdd13d93,0x3de2bd71,0x3de73d5b,0x3d7cbddf,0xbd383def,
0xbdb53d80,0x3dbebdac,0xbdb1bdb9,0x3da73dc2,0xbd153df5,0x3ddcbd84,0xbd89bdd8,0x3d7c3ddf,0xbd713de2,0x3df1bd2c,0xbd38bdef,0x3d213df3,0xbda23dc6,0x3dfdbc96,0xbcafbdfc,0x3c7b3dfe,
0x3db53d80,0xbddc3d84,0x3d9d3dca,0xbd4fbdea,0xbdff3c49,0xbde7bd5b,0xbd213df3,0x3d89bdd8,0xbda2bdc6,0xbc96bdfd,0xbdf73d09,0x3e00bb49,0x3d15bdf5,0x3dbebdac,0xbdc2bda7,0x3d933dd1,
0xbdb53d80,0x3df1bd2c,0xbd89bdd8,0x3c7b3dfe,0xbd71bde2,0x3c963dfd,0x3defbd38,0xbdffbc17,0x3df5bd15,0xbe00bbc9,0x3caf3dfc,0x3d09bdf7,0x3c493dff,0x3cf9bdf8,0xbe00bb49,0x3de53d66,
0x3db53d80,0xbdfd3c96,0x3d663de5,0x3cafbdfc,0x3da2bdc6,0x3dbebdac,0xbddfbd7c,0x3d4f3dea,0xbc493dff,0xbcf93df8,0x3dffbc17,0xbdd8bd89,0xbd71bde2,0xbd2cbdf1,0xbdca3d9d,0x3e00bb49,
0xbdb53d80,0x3e003bc9,0xbd38bdef,0xbd663de5,0x3df53d15,0xbdf8bcf9,0x3caf3dfc,0x3d9dbdca,0xbde2bd71,0x3de73d5b,0x3b49be00,0xbdc23da7,0x3dc63da2,0xbdcebd98,0xbce03dfa,0x3ddfbd7c,
0x3db53d80,0xbdf8bcf9,0x3d093df7,0x3db1bdb9,0x3c493dff,0x3d2c3df1,0x3da7bdc2,0xbdfcbcaf,0x3dc6bda2,0x3d98bdce,0xbdfebc7b,0x3d4f3dea,0xbdf5bd15,0xbe00bbc9,0x3d663de5,0x3d89bdd8,
0xbdb53d80,0x3de73d5b,0xbcafbdfc,0xbddf3d7c,0xbde23d71,0x3d98bdce,0xbe00bb49,0x3d213df3,0x3d153df5,0xbdacbdbe,0xbce03dfa,0x3dfebc7b,0x3dffbc49,0xbddc3d84,0x3dea3d4f,0x3c17bdff,
0x3db53d80,0xbdcebd98,0x3c173dff,0x3dfabce0,0xbdc6bda2,0xbe00bbc9,0x3d9d3dca,0x3db1bdb9,0xbdffbc49,0xbddc3d84,0x3df33d21,0x3cafbdfc,0xbde23d71,0xbd5b3de7,0x3df7bd09,0xbd4fbdea,
0xbdb53d80,0x3dac3dbe,0x3b49be00,0xbdffbc17,0x3d15bdf5,0x3d843ddc,0x3ce0bdfa,0xbdf7bd09,0x3d71bde2,0x3d2c3df1,0x3d4fbdea,0xbde5bd66,0x3da2bdc6,0x3c963dfd,0x3d93bdd1,0xbdcabd9d,
0x3db53d80,0xbd84bddc,0xbc7b3dfe,0x3def3d38,0x3dffbc49,0x3d5bbde7,0xbde53d66,0x3ce03dfa,0x3da23dc6,0x3dfdbc96,0xbddfbd7c,0xbdb13db9,0xbd153df5,0x3dac3dbe,0xbc17bdff,0xbdfcbcaf,
0xbdb53d80,0x3d2c3df1,0x3ce0bdfa,0xbdcabd9d,0x3d713de2,0xbdfd3c96,0x3dea3d4f,0x3dc2bda7,0xbdf53d15,0x3bc9be00,0xbd933dd1,0x3d7c3ddf,0xbc49bdff,0x3df83cf9,0xbdb1bdb9,0xbdf33d21,
0x3db53d80,0xbc96bdfd,0xbd213df3,0x3d933dd1,0xbda23dc6,0x3dac3dbe,0xbd09bdf7,0xbdefbd38,0x3c49bdff,0xbdf8bcf9,0x3dc23da7,0x3dfabce0,0x3d713de2,0x3df1bd2c,0xbdfebc7b,0xbdb13db9,
0xbdb53d80,0xbbc93e00,0x3d4fbdea,0xbd21bdf3,0xbdf5bd15,0x3cf9bdf8,0xbd933dd1,0x3c7b3dfe,0x3de23d71,0xbd5b3de7,0x3db9bdb1,0x3c17bdff,0xbdc6bda2,0x3d98bdce,0xbdd83d89,0xbd093df7,
0x3db53d80,0x3cf9bdf8,0xbd7c3ddf,0x3b493e00,0xbc49bdff,0xbdf13d2c,0x3dffbc17,0x3dd1bd93,0xbdc63da2,0x3dce3d98,0xbd9dbdca,0xbdefbd38,0x3df53d15,0x3bc9be00,0xbd213df3,0x3ce03dfa,
0xbdb53d80,0xbd5b3de7,0x3d93bdd1,0x3d09bdf7,0x3de2bd71,0x3dce3d98,0xbdb1bdb9,0xbde5bd66,0xbd15bdf5,0x3dbebdac,0xbdd83d89,0xbd9d3dca,0xbdff3c49,0xbd84bddc,0x3d383def,0x3da73dc2,
0x3db53d80,0x3d98bdce,0xbda73dc2,0xbd893dd8,0x3dc63da2,0x3bc9be00,0xbc7b3dfe,0x3b493e00,0x3dff3c49,0xbd84bddc,0x3d663de5,0x3d933dd1,0x3de2bd71,0xbde7bd5b,0x3ddf3d7c,0x3def3d38,
0xbcc83dfb,0xbc493dff,0xbbc93e00,0xbc963dfd,0xbd443ded,0xbd713de2,0xbd5b3de7,0xbd843ddc,0xbdb53db5,0xbdc63da2,0xbdbe3dac,0xbdce3d98,0xbded3d44,0xbdf53d15,0xbdf13d2c,0xbdf83cf9,
0xbd8e3dd5,0xbd153df5,0xbc963dfd,0xbd5b3de7,0xbded3d44,0xbdff3c49,0xbdf83cf9,0xbe00bbc9,0xbdb5bdb5,0xbd71bde2,0xbd98bdce,0xbd2cbdf1,0x3d44bded,0x3da2bdc6,0x3d84bddc,0x3dbebdac,
0xbdd53d8e,0xbd713de2,0xbcf93df8,0xbdac3dbe,0xbdedbd44,0xbda2bdc6,0xbdcebd98,0xbd5bbde7,0x3db5bdb5,0x3df5bd15,0x3ddcbd84,0x3e00bbc9,0x3d443ded,0xbc493dff,0x3c963dfd,0xbd2c3df1,
0xbdfb3cc8,0xbda23dc6,0xbd2c3df1,0xbddc3d84,0xbd44bded,0x3d15bdf5,0xbbc9be00,0x3d98bdce,0x3db53db5,0x3c493dff,0x3d5b3de7,0xbcf93df8,0xbdedbd44,0xbd71bde2,0xbdbebdac,0xbc96bdfd,
0xbdfbbcc8,0xbdc63da2,0xbd5b3de7,0xbdf83cf9,0x3d44bded,0x3df5bd15,0x3dbebdac,0x3dfd3c96,0xbdb53db5,0xbdffbc49,0xbdf13d2c,0xbddcbd84,0x3dedbd44,0x3de23d71,0x3e003bc9,0x3d983dce,
0xbdd5bd8e,0xbde23d71,0xbd843ddc,0xbe00bbc9,0x3dedbd44,0x3dc63da2,0x3dfd3c96,0x3d2c3df1,0xbdb5bdb5,0x3d15bdf5,0xbcf9bdf8,0x3dbebdac,0xbd443ded,0xbdff3c49,0xbdce3d98,0xbde7bd5b,
0xbd8ebdd5,0xbdf53d15,0xbd983dce,0xbdf1bd2c,0x3ded3d44,0xbc493dff,0x3d843ddc,0xbdac3dbe,0x3db5bdb5,0x3de23d71,0x3dfdbc96,0x3d5b3de7,0xbd44bded,0x3dc6bda2,0x3cf9bdf8,0x3e00bbc9,
0xbcc8bdfb,0xbdff3c49,0xbdac3dbe,0xbdcebd98,0x3d443ded,0xbde23d71,0xbd2c3df1,0xbdf8bcf9,0x3db53db5,0xbda23dc6,0x3bc93e00,0xbdfd3c96,0x3ded3d44,0xbd153df5,0x3d5b3de7,0xbddc3d84,
0x3cc8bdfb,0xbdffbc49,0xbdbe3dac,0xbd98bdce,0xbd443ded,0xbde2bd71,0xbdf13d2c,0xbcf9bdf8,0xbdb53db5,0xbda2bdc6,0xbe00bbc9,0x3c96bdfd,0xbded3d44,0xbd15bdf5,0xbde7bd5b,0x3d84bddc,
0x3d8ebdd5,0xbdf5bd15,0xbdce3d98,0xbd2cbdf1,0xbded3d44,0xbc49bdff,0xbddcbd84,0x3dbebdac,0xbdb5bdb5,0x3de2bd71,0x3c96bdfd,0x3de73d5b,0x3d44bded,0x3dc63da2,0x3df8bcf9,0xbbc93e00,
0x3dd5bd8e,0xbde2bd71,0xbddc3d84,0xbbc9be00,0xbdedbd44,0x3dc6bda2,0xbc96bdfd,0x3df13d2c,0x3db5bdb5,0x3d153df5,0x3df83cf9,0xbdac3dbe,0x3d443ded,0xbdffbc49,0xbd983dce,0xbd5bbde7,
0x3dfbbcc8,0xbdc6bda2,0xbde73d5b,0x3cf9bdf8,0xbd44bded,0x3df53d15,0x3dacbdbe,0x3c963dfd,0x3db53db5,0xbdff3c49,0xbd2c3df1,0xbd84bddc,0xbdedbd44,0x3de2bd71,0xbbc9be00,0x3dce3d98,
0x3dfb3cc8,0xbda2bdc6,0xbdf13d2c,0x3d84bddc,0x3d44bded,0x3d153df5,0x3e003bc9,0xbdce3d98,0xbdb53db5,0x3c49bdff,0xbde7bd5b,0x3df8bcf9,0x3dedbd44,0xbd713de2,0x3dac3dbe,0xbdfdbc96,
0x3dd53d8e,0xbd71bde2,0xbdf83cf9,0x3dbebdac,0x3dedbd44,0xbda23dc6,0x3d983dce,0xbde7bd5b,0xbdb5bdb5,0x3df53d15,0x3d84bddc,0xbbc93e00,0xbd443ded,0xbc49bdff,0xbdfdbc96,0x3df1bd2c,
0x3d8e3dd5,0xbd15bdf5,0xbdfd3c96,0x3de7bd5b,0x3ded3d44,0xbdffbc49,0xbcf93df8,0xbbc9be00,0x3db5bdb5,0xbd713de2,0x3dce3d98,0xbdf1bd2c,0xbd44bded,0x3da23dc6,0x3ddcbd84,0xbdac3dbe,
0x3cc83dfb,0xbc49bdff,0xbe003bc9,0x3dfdbc96,0x3d443ded,0xbd71bde2,0xbde73d5b,0x3ddcbd84,0x3db53db5,0xbdc6bda2,0xbdac3dbe,0x3d98bdce,0x3ded3d44,0xbdf5bd15,0xbd2c3df1,0x3cf9bdf8,
0xbcc83dfb,0x3c49bdff,0xbe00bbc9,0x3dfd3c96,0xbd443ded,0x3d71bde2,0xbde7bd5b,0x3ddc3d84,0xbdb53db5,0x3dc6bda2,0xbdacbdbe,0x3d983dce,0xbded3d44,0x3df5bd15,0xbd2cbdf1,0x3cf93df8,
0xbd8e3dd5,0x3d15bdf5,0xbdfdbc96,0x3de73d5b,0xbded3d44,0x3dffbc49,0xbcf9bdf8,0xbbc93e00,0xbdb5bdb5,0x3d713de2,0x3dcebd98,0xbdf13d2c,0x3d44bded,0xbda23dc6,0x3ddc3d84,0xbdacbdbe,
0xbdd53d8e,0x3d71bde2,0xbdf8bcf9,0x3dbe3dac,0xbdedbd44,0x3da23dc6,0x3d98bdce,0xbde73d5b,0x3db5bdb5,0xbdf53d15,0x3d843ddc,0xbbc9be00,0x3d443ded,0x3c49bdff,0xbdfd3c96,0x3df13d2c,
0xbdfb3cc8,0x3da2bdc6,0xbdf1bd2c,0x3d843ddc,0xbd44bded,0xbd153df5,0x3e00bbc9,0xbdcebd98,0x3db53db5,0xbc49bdff,0xbde73d5b,0x3df83cf9,0xbdedbd44,0x3d713de2,0x3dacbdbe,0xbdfd3c96,
0xbdfbbcc8,0x3dc6bda2,0xbde7bd5b,0x3cf93df8,0x3d44bded,0xbdf53d15,0x3dac3dbe,0x3c96bdfd,0xbdb53db5,0x3dff3c49,0xbd2cbdf1,0xbd843ddc,0x3dedbd44,0xbde2bd71,0xbbc93e00,0x3dcebd98,
0xbdd5bd8e,0x3de2bd71,0xbddcbd84,0xbbc93e00,0x3dedbd44,0xbdc6bda2,0xbc963dfd,0x3df1bd2c,0xbdb5bdb5,0xbd153df5,0x3df8bcf9,0xbdacbdbe,0xbd443ded,0x3dffbc49,0xbd98bdce,0xbd5b3de7,
0xbd8ebdd5,0x3df5bd15,0xbdcebd98,0xbd2c3df1,0x3ded3d44,0x3c49bdff,0xbddc3d84,0x3dbe3dac,0x3db5bdb5,0xbde2bd71,0x3c963dfd,0x3de7bd5b,0xbd44bded,0xbdc63da2,0x3df83cf9,0xbbc9be00,
0xbcc8bdfb,0x3dffbc49,0xbdbebdac,0xbd983dce,0x3d443ded,0x3de2bd71,0xbdf1bd2c,0xbcf93df8,0x3db53db5,0x3da2bdc6,0xbe003bc9,0x3c963dfd,0x3ded3d44,0x3d15bdf5,0xbde73d5b,0x3d843ddc,
0x3cc8bdfb,0x3dff3c49,0xbdacbdbe,0xbdce3d98,0xbd443ded,0x3de23d71,0xbd2cbdf1,0xbdf83cf9,0xbdb53db5,0x3da23dc6,0x3bc9be00,0xbdfdbc96,0xbded3d44,0x3d153df5,0x3d5bbde7,0xbddcbd84,
0x3d8ebdd5,0x3df53d15,0xbd98bdce,0xbdf13d2c,0xbded3d44,0x3c493dff,0x3d84bddc,0xbdacbdbe,0xbdb5bdb5,0xbde23d71,0x3dfd3c96,0x3d5bbde7,0x3d44bded,0xbdc6bda2,0x3cf93df8,0x3e003bc9,
0x3dd5bd8e,0x3de23d71,0xbd84bddc,0xbe003bc9,0xbdedbd44,0xbdc63da2,0x3dfdbc96,0x3d2cbdf1,0x3db5bdb5,0xbd15bdf5,0xbcf93df8,0x3dbe3dac,0x3d443ded,0x3dff3c49,0xbdcebd98,0xbde73d5b,
0x3dfbbcc8,0x3dc63da2,0xbd5bbde7,0xbdf8bcf9,0xbd44bded,0xbdf5bd15,0x3dbe3dac,0x3dfdbc96,0x3db53db5,0x3dffbc49,0xbdf1bd2c,0xbddc3d84,0xbdedbd44,0xbde23d71,0x3e00bbc9,0x3d98bdce,
0x3dfb3cc8,0x3da23dc6,0xbd2cbdf1,0xbddcbd84,0x3d44bded,0xbd15bdf5,0xbbc93e00,0x3d983dce,0xbdb53db5,0xbc493dff,0x3d5bbde7,0xbcf9bdf8,0x3dedbd44,0x3d71bde2,0xbdbe3dac,0xbc963dfd,
0x3dd53d8e,0x3d713de2,0xbcf9bdf8,0xbdacbdbe,0x3dedbd44,0x3da2bdc6,0xbdce3d98,0xbd5b3de7,0xbdb5bdb5,0xbdf5bd15,0x3ddc3d84,0x3e003bc9,0xbd443ded,0x3c493dff,0x3c96bdfd,0xbd2cbdf1,
0x3d8e3dd5,0x3d153df5,0xbc96bdfd,0xbd5bbde7,0x3ded3d44,0x3dff3c49,0xbdf8bcf9,0xbe003bc9,0x3db5bdb5,0x3d71bde2,0xbd983dce,0xbd2c3df1,0xbd44bded,0xbda2bdc6,0x3d843ddc,0x3dbe3dac,
0x3cc83dfb,0x3c493dff,0xbbc9be00,0xbc96bdfd,0x3d443ded,0x3d713de2,0xbd5bbde7,0xbd84bddc,0x3db53db5,0x3dc63da2,0xbdbebdac,0xbdcebd98,0x3ded3d44,0x3df53d15,0xbdf1bd2c,0xbdf8bcf9,
0xbd803d80,0xbdffbc49,0xbe00bbc9,0xbdfdbc96,0xbd8e3dd5,0xbde2bd71,0xbde7bd5b,0xbddcbd84,0xbdd53d8e,0xbda2bdc6,0xbdacbdbe,0xbd98bdce,0xbdfb3cc8,0xbd15bdf5,0xbd2cbdf1,0xbcf9bdf8,
0x3d803d80,0x3df53d15,0x3dfd3c96,0x3de73d5b,0xbdfbbcc8,0x3c493dff,0x3cf93df8,0xbbc93e00,0xbcc8bdfb,0xbde23d71,0xbdce3d98,0xbdf13d2c,0x3dd5bd8e,0xbdc6bda2,0xbddcbd84,0xbdacbdbe,
0xbd803d80,0xbde2bd71,0xbdf8bcf9,0xbdbebdac,0xbcc8bdfb,0x3dc6bda2,0x3d98bdce,0x3de7bd5b,0x3dfb3cc8,0x3d153df5,0x3d843ddc,0x3bc93e00,0xbd8e3dd5,0xbdffbc49,0xbdfd3c96,0xbdf1bd2c,
0x3d803d80,0x3dc63da2,0x3df13d2c,0x3d843ddc,0x3dd5bd8e,0xbdf5bd15,0xbe003bc9,0xbdcebd98,0xbd8e3dd5,0x3dffbc49,0x3de7bd5b,0x3df83cf9,0x3cc8bdfb,0xbde23d71,0xbdac3dbe,0xbdfd3c96,
0xbd803d80,0xbda2bdc6,0xbde7bd5b,0xbcf9bdf8,0x3dd53d8e,0x3d153df5,0x3dac3dbe,0xbc963dfd,0xbd8ebdd5,0x3c49bdff,0xbd2cbdf1,0x3d84bddc,0x3cc83dfb,0xbd713de2,0xbbc93e00,0xbdce3d98,
0x3d803d80,0x3d713de2,0x3ddc3d84,0xbbc93e00,0xbcc83dfb,0x3da2bdc6,0x3c96bdfd,0x3df1bd2c,0x3dfbbcc8,0xbdf5bd15,0xbdf83cf9,0xbdacbdbe,0xbd8ebdd5,0x3c493dff,0x3d983dce,0xbd5b3de7,
0xbd803d80,0xbd15bdf5,0xbdcebd98,0x3d2cbdf1,0xbdfb3cc8,0xbdffbc49,0xbddc3d84,0xbdbebdac,0xbcc83dfb,0xbd713de2,0x3c963dfd,0xbde73d5b,0x3dd53d8e,0x3da23dc6,0x3df83cf9,0x3bc93e00,
0x3d803d80,0x3c493dff,0x3dbe3dac,0xbd983dce,0xbd8ebdd5,0x3d713de2,0x3df13d2c,0xbcf93df8,0xbdd5bd8e,0x3dc63da2,0x3e00bbc9,0x3c963dfd,0xbdfbbcc8,0x3df53d15,0x3de7bd5b,0x3d843ddc,
0xbd803d80,0x3c49bdff,0xbdacbdbe,0x3dcebd98,0x3d8ebdd5,0x3d71bde2,0xbd2cbdf1,0x3df8bcf9,0x3dd5bd8e,0x3dc6bda2,0x3bc9be00,0x3dfd3c96,0x3dfbbcc8,0x3df5bd15,0x3d5bbde7,0x3ddc3d84,
0x3d803d80,0xbd153df5,0x3d983dce,0xbdf13d2c,0x3dfb3cc8,0xbdff3c49,0xbd843ddc,0xbdacbdbe,0x3cc83dfb,0xbd71bde2,0xbdfdbc96,0x3d5bbde7,0xbdd53d8e,0x3da2bdc6,0xbcf9bdf8,0x3e003bc9,
0xbd803d80,0x3d71bde2,0xbd84bddc,0x3e00bbc9,0x3cc83dfb,0x3da23dc6,0x3dfdbc96,0xbd2c3df1,0xbdfbbcc8,0xbdf53d15,0xbcf93df8,0xbdbebdac,0x3d8ebdd5,0x3c49bdff,0xbdcebd98,0x3de7bd5b,
0x3d803d80,0xbda23dc6,0x3d5b3de7,0xbdf8bcf9,0xbdd53d8e,0x3d15bdf5,0xbdbebdac,0x3dfdbc96,0x3d8ebdd5,0x3c493dff,0x3df13d2c,0xbddc3d84,0xbcc83dfb,0xbd71bde2,0xbe003bc9,0x3d98bdce,
0xbd803d80,0x3dc6bda2,0xbd2cbdf1,0x3ddc3d84,0xbdd5bd8e,0xbdf53d15,0xbbc93e00,0xbd98bdce,0x3d8e3dd5,0x3dff3c49,0x3d5bbde7,0x3cf93df8,0xbcc8bdfb,0xbde2bd71,0xbdbe3dac,0x3c96bdfd,
0x3d803d80,0xbde23d71,0x3cf93df8,0xbdacbdbe,0x3cc8bdfb,0x3dc63da2,0x3dcebd98,0xbd5b3de7,0xbdfb3cc8,0x3d15bdf5,0xbddcbd84,0x3e003bc9,0x3d8e3dd5,0xbdff3c49,0xbc963dfd,0xbd2cbdf1,
0xbd803d80,0x3df5bd15,0xbc96bdfd,0x3d5b3de7,0x3dfbbcc8,0x3c49bdff,0xbdf8bcf9,0x3e00bbc9,0x3cc8bdfb,0xbde2bd71,0xbd983dce,0x3d2cbdf1,0xbdd5bd8e,0xbdc63da2,0x3d843ddc,0xbdbebdac,
0x3d803d80,0xbdff3c49,0x3bc93e00,0xbc96bdfd,0x3d8e3dd5,0xbde23d71,0x3d5b3de7,0xbd84bddc,0x3dd53d8e,0xbda23dc6,0x3dbe3dac,0xbdcebd98,0x3dfb3cc8,0xbd153df5,0x3df13d2c,0xbdf8bcf9,
0xbd803d80,0x3dff3c49,0x3bc9be00,0xbc963dfd,0xbd8e3dd5,0x3de23d71,0x3d5bbde7,0xbd843ddc,0xbdd53d8e,0x3da23dc6,0x3dbebdac,0xbdce3d98,0xbdfb3cc8,0x3d153df5,0x3df1bd2c,0xbdf83cf9,
0x3d803d80,0xbdf5bd15,0xbc963dfd,0x3d5bbde7,0xbdfbbcc8,0xbc49bdff,0xbdf83cf9,0x3e003bc9,0xbcc8bdfb,0x3de2bd71,0xbd98bdce,0x3d2c3df1,0x3dd5bd8e,0x3dc63da2,0x3d84bddc,0xbdbe3dac,
0xbd803d80,0x3de23d71,0x3cf9bdf8,0xbdac3dbe,0xbcc8bdfb,0xbdc63da2,0x3dce3d98,0xbd5bbde7,0x3dfb3cc8,0xbd15bdf5,0xbddc3d84,0x3e00bbc9,0xbd8e3dd5,0x3dff3c49,0xbc96bdfd,0xbd2c3df1,
0x3d803d80,0xbdc6bda2,0xbd2c3df1,0x3ddcbd84,0x3dd5bd8e,0x3df53d15,0xbbc9be00,0xbd983dce,0xbd8e3dd5,0xbdff3c49,0x3d5b3de7,0x3cf9bdf8,0x3cc8bdfb,0x3de2bd71,0xbdbebdac,0x3c963dfd,
0xbd803d80,0x3da23dc6,0x3d5bbde7,0xbdf83cf9,0x3dd53d8e,0xbd15bdf5,0xbdbe3dac,0x3dfd3c96,0xbd8ebdd5,0xbc493dff,0x3df1bd2c,0xbddcbd84,0x3cc83dfb,0x3d71bde2,0xbe00bbc9,0x3d983dce,
0x3d803d80,0xbd71bde2,0xbd843ddc,0x3e003bc9,0xbcc83dfb,0xbda23dc6,0x3dfd3c96,0xbd2cbdf1,0x3dfbbcc8,0x3df53d15,0xbcf9bdf8,0xbdbe3dac,0xbd8ebdd5,0xbc49bdff,0xbdce3d98,0x3de73d5b,
0xbd803d80,0x3d153df5,0x3d98bdce,0xbdf1bd2c,0xbdfb3cc8,0x3dff3c49,0xbd84bddc,0xbdac3dbe,0xbcc83dfb,0x3d71bde2,0xbdfd3c96,0x3d5b3de7,0x3dd53d8e,0xbda2bdc6,0xbcf93df8,0x3e00bbc9,
0x3d803d80,0xbc49bdff,0xbdac3dbe,0x3dce3d98,0xbd8ebdd5,0xbd71bde2,0xbd2c3df1,0x3df83cf9,0xbdd5bd8e,0xbdc6bda2,0x3bc93e00,0x3dfdbc96,0xbdfbbcc8,0xbdf5bd15,0x3d5b3de7,0x3ddcbd84,
0xbd803d80,0xbc493dff,0x3dbebdac,0xbd98bdce,0x3d8ebdd5,0xbd713de2,0x3df1bd2c,0xbcf9bdf8,0x3dd5bd8e,0xbdc63da2,0x3e003bc9,0x3c96bdfd,0x3dfbbcc8,0xbdf53d15,0x3de73d5b,0x3d84bddc,
0x3d803d80,0x3d15bdf5,0xbdce3d98,0x3d2c3df1,0x3dfb3cc8,0x3dffbc49,0xbddcbd84,0xbdbe3dac,0x3cc83dfb,0x3d713de2,0x3c96bdfd,0xbde7bd5b,0xbdd53d8e,0xbda23dc6,0x3df8bcf9,0x3bc9be00,
0xbd803d80,0xbd713de2,0x3ddcbd84,0xbbc9be00,0x3cc83dfb,0xbda2bdc6,0x3c963dfd,0x3df13d2c,0xbdfbbcc8,0x3df5bd15,0xbdf8bcf9,0xbdac3dbe,0x3d8ebdd5,0xbc493dff,0x3d98bdce,0xbd5bbde7,
0x3d803d80,0x3da2bdc6,0xbde73d5b,0xbcf93df8,0xbdd53d8e,0xbd153df5,0x3dacbdbe,0xbc96bdfd,0x3d8ebdd5,0xbc49bdff,0xbd2c3df1,0x3d843ddc,0xbcc83dfb,0x3d713de2,0xbbc9be00,0xbdcebd98,
0xbd803d80,0xbdc63da2,0x3df1bd2c,0x3d84bddc,0xbdd5bd8e,0x3df5bd15,0xbe00bbc9,0xbdce3d98,0x3d8e3dd5,0xbdffbc49,0x3de73d5b,0x3df8bcf9,0xbcc8bdfb,0x3de23d71,0xbdacbdbe,0xbdfdbc96,
0x3d803d80,0x3de2bd71,0xbdf83cf9,0xbdbe3dac,0x3cc8bdfb,0xbdc6bda2,0x3d983dce,0x3de73d5b,0xbdfb3cc8,0xbd153df5,0x3d84bddc,0x3bc9be00,0x3d8e3dd5,0x3dffbc49,0xbdfdbc96,0xbdf13d2c,
0xbd803d80,0xbdf53d15,0x3dfdbc96,0x3de7bd5b,0x3dfbbcc8,0xbc493dff,0x3cf9bdf8,0xbbc9be00,0x3cc8bdfb,0x3de23d71,0xbdcebd98,0xbdf1bd2c,0xbdd5bd8e,0x3dc6bda2,0xbddc3d84,0xbdac3dbe,
0x3d803d80,0x3dffbc49,0xbe003bc9,0xbdfd3c96,0x3d8e3dd5,0x3de2bd71,0xbde73d5b,0xbddc3d84,0x3dd53d8e,0x3da2bdc6,0xbdac3dbe,0xbd983dce,0x3dfb3cc8,0x3d15bdf5,0xbd2c3df1,0xbcf93df8,
0xbd153df5,0xbc963dfd,0xbc173dff,0xbce03dfa,0xbd8e3dd5,0xbdac3dbe,0xbd9d3dca,0xbdb93db1,0xbded3d44,0xbdf83cf9,0xbdf33d21,0xbdfc3caf,0xbdfbbcc8,0xbdf1bd2c,0xbdf7bd09,0xbdeabd4f,
0xbda23dc6,0xbd2c3df1,0xbcaf3dfc,0xbd7c3ddf,0xbdfb3cc8,0xbdfdbc96,0xbe003b49,0xbdf3bd21,0xbd44bded,0xbbc9be00,0xbce0bdfa,0x3c7bbdfe,0x3dd5bd8e,0x3df8bcf9,0x3deabd4f,0x3dffbc17,
0xbde23d71,0xbd843ddc,0xbd093df7,0xbdb93db1,0xbdd5bd8e,0xbd5bbde7,0xbda7bdc2,0xbcafbdfc,0x3dedbd44,0x3dfd3c96,0x3dfebc7b,0x3dea3d4f,0xbcc83dfb,0xbdac3dbe,0xbd663de5,0xbdd83d89,
0xbdff3c49,0xbdac3dbe,0xbd383def,0xbde53d66,0xbcc8bdfb,0x3d84bddc,0x3cafbdfc,0x3dcabd9d,0x3d443ded,0xbd2c3df1,0x3b493e00,0xbda73dc2,0xbd8ebdd5,0x3c96bdfd,0xbce0bdfa,0x3d7cbddf,
0xbdf5bd15,0xbdce3d98,0xbd663de5,0xbdfc3caf,0x3d8ebdd5,0x3e00bbc9,0x3ddfbd7c,0x3dea3d4f,0xbded3d44,0xbddcbd84,0xbdffbc17,0xbd89bdd8,0x3dfb3cc8,0x3d5b3de7,0x3dca3d9d,0xbb493e00,
0xbdc6bda2,0xbde73d5b,0xbd893dd8,0xbdfebc7b,0x3dfbbcc8,0x3d983dce,0x3def3d38,0x3c173dff,0xbd44bded,0x3dacbdbe,0x3cafbdfc,0x3df7bd09,0xbdd53d8e,0xbddcbd84,0xbe003b49,0xbd66bde5,
0xbd71bde2,0xbdf83cf9,0xbd9d3dca,0xbdeabd4f,0x3dd53d8e,0xbd2c3df1,0x3d213df3,0xbdd83d89,0x3dedbd44,0x3d983dce,0x3df73d09,0xbb493e00,0x3cc8bdfb,0x3e00bbc9,0x3dc2bda7,0x3dd13d93,
0xbc49bdff,0xbe003bc9,0xbdb13db9,0xbdc2bda7,0x3cc83dfb,0xbdf83cf9,0xbd893dd8,0xbddfbd7c,0x3d443ded,0xbde73d5b,0xbd383def,0xbdf3bd21,0x3d8e3dd5,0xbdce3d98,0xbcaf3dfc,0xbdfebc7b,
0x3d15bdf5,0xbdfdbc96,0xbdc23da7,0xbd89bdd8,0xbd8e3dd5,0xbdbebdac,0xbdfe3c7b,0x3b49be00,0xbded3d44,0xbcf9bdf8,0xbde5bd66,0x3d93bdd1,0xbdfbbcc8,0x3d2cbdf1,0xbd7cbddf,0x3defbd38,
0x3da2bdc6,0xbdf1bd2c,0xbdd13d93,0xbd09bdf7,0xbdfb3cc8,0x3c96bdfd,0xbdb9bdb1,0x3de5bd66,0xbd44bded,0x3e00bbc9,0x3d89bdd8,0x3d9d3dca,0x3dd5bd8e,0x3cf93df8,0x3def3d38,0xbda73dc2,
0x3de2bd71,0xbddcbd84,0xbddf3d7c,0x3b49be00,0xbdd5bd8e,0x3de7bd5b,0x3c17bdff,0x3dd13d93,0x3dedbd44,0xbc963dfd,0x3dca3d9d,0xbdef3d38,0xbcc83dfb,0xbdbebdac,0xbdf33d21,0x3ce0bdfa,
0x3dffbc49,0xbdbebdac,0xbdea3d4f,0x3d21bdf3,0xbcc8bdfb,0x3ddc3d84,0x3dd1bd93,0xbc7b3dfe,0x3d443ded,0xbdf1bd2c,0xbdb13db9,0xbc17bdff,0xbd8ebdd5,0x3dfd3c96,0x3d89bdd8,0x3d093df7,
0x3df53d15,0xbd98bdce,0xbdf33d21,0x3d93bdd1,0x3d8ebdd5,0x3bc93e00,0x3df73d09,0xbdef3d38,0xbded3d44,0x3d84bddc,0xbda7bdc2,0x3dfa3ce0,0x3dfb3cc8,0xbde73d5b,0x3c7b3dfe,0xbdb1bdb9,
0x3dc63da2,0xbd5bbde7,0xbdfa3ce0,0x3dcabd9d,0x3dfbbcc8,0xbdce3d98,0x3d4f3dea,0xbdc2bda7,0xbd44bded,0x3dbe3dac,0x3dd1bd93,0xbd7c3ddf,0xbdd53d8e,0x3d84bddc,0xbdb9bdb1,0x3df33d21,
0x3d713de2,0xbcf9bdf8,0xbdfe3c7b,0x3defbd38,0x3dd53d8e,0xbdf1bd2c,0xbd663de5,0x3ce0bdfa,0x3dedbd44,0xbdce3d98,0x3d7c3ddf,0xbdb1bdb9,0x3cc8bdfb,0x3bc93e00,0x3dff3c17,0xbdfc3caf,
0x3c493dff,0xbbc9be00,0xbe003b49,0x3dffbc17,0x3cc83dfb,0xbcf9bdf8,0xbdfa3ce0,0x3df7bd09,0x3d443ded,0xbd5bbde7,0xbdea3d4f,0x3de5bd66,0x3d8e3dd5,0xbd98bdce,0xbdd13d93,0x3dcabd9d,
0xbd153df5,0x3c96bdfd,0xbdffbc17,0x3dfa3ce0,0xbd8e3dd5,0x3dacbdbe,0xbdcabd9d,0x3db13db9,0xbded3d44,0x3df8bcf9,0xbd21bdf3,0x3caf3dfc,0xbdfbbcc8,0x3df13d2c,0x3d09bdf7,0xbd4f3dea,
0xbda23dc6,0x3d2cbdf1,0xbdfcbcaf,0x3ddf3d7c,0xbdfb3cc8,0x3dfd3c96,0xbb49be00,0xbd213df3,0xbd44bded,0x3bc93e00,0x3dfabce0,0xbdfebc7b,0x3dd5bd8e,0xbdf83cf9,0x3d4f3dea,0xbc17bdff,
0xbde23d71,0x3d84bddc,0xbdf7bd09,0x3db13db9,0xbdd5bd8e,0x3d5b3de7,0x3dc2bda7,0xbdfc3caf,0x3dedbd44,0xbdfdbc96,0x3c7b3dfe,0x3d4fbdea,0xbcc83dfb,0x3dacbdbe,0xbde5bd66,0x3d893dd8,
0xbdff3c49,0x3dacbdbe,0xbdefbd38,0x3d663de5,0xbcc8bdfb,0xbd843ddc,0x3dfc3caf,0xbd9dbdca,0x3d443ded,0x3d2cbdf1,0xbe003b49,0x3dc23da7,0xbd8ebdd5,0xbc963dfd,0x3dfabce0,0xbddfbd7c,
0xbdf5bd15,0x3dcebd98,0xbde5bd66,0x3caf3dfc,0x3d8ebdd5,0xbe003bc9,0x3d7c3ddf,0x3d4fbdea,0xbded3d44,0x3ddc3d84,0x3c17bdff,0xbdd83d89,0x3dfb3cc8,0xbd5bbde7,0xbd9d3dca,0x3e003b49,
0xbdc6bda2,0x3de7bd5b,0xbdd8bd89,0xbc7b3dfe,0x3dfbbcc8,0xbd98bdce,0xbd383def,0x3dffbc17,0xbd44bded,0xbdac3dbe,0x3dfc3caf,0xbd09bdf7,0xbdd53d8e,0x3ddc3d84,0xbb49be00,0xbde53d66,
0xbd71bde2,0x3df8bcf9,0xbdcabd9d,0xbd4f3dea,0x3dd53d8e,0x3d2cbdf1,0xbdf33d21,0x3d893dd8,0x3dedbd44,0xbd98bdce,0xbd093df7,0x3e003b49,0x3cc8bdfb,0xbe003bc9,0x3da73dc2,0x3d93bdd1,
0xbc49bdff,0x3e00bbc9,0xbdb9bdb1,0xbda73dc2,0x3cc83dfb,0x3df8bcf9,0xbdd8bd89,0xbd7c3ddf,0x3d443ded,0x3de7bd5b,0xbdefbd38,0xbd213df3,0x3d8e3dd5,0x3dcebd98,0xbdfcbcaf,0xbc7b3dfe,
0x3d15bdf5,0x3dfd3c96,0xbda7bdc2,0xbdd83d89,0xbd8e3dd5,0x3dbe3dac,0xbc7bbdfe,0xbe00bb49,0xbded3d44,0x3cf93df8,0x3d66bde5,0xbdd1bd93,0xbdfbbcc8,0xbd2c3df1,0x3ddfbd7c,0xbd38bdef,
0x3da2bdc6,0x3df13d2c,0xbd93bdd1,0xbdf73d09,0xbdfb3cc8,0xbc963dfd,0x3db1bdb9,0xbd66bde5,0xbd44bded,0xbe003bc9,0x3dd83d89,0x3dcabd9d,0x3dd5bd8e,0xbcf9bdf8,0xbd383def,0x3dc23da7,
0x3de2bd71,0x3ddc3d84,0xbd7cbddf,0xbe00bb49,0xbdd5bd8e,0xbde73d5b,0x3dff3c17,0x3d93bdd1,0x3dedbd44,0x3c96bdfd,0xbd9d3dca,0x3d383def,0xbcc83dfb,0x3dbe3dac,0xbd21bdf3,0xbdfabce0,
0x3dffbc49,0x3dbe3dac,0xbd4fbdea,0xbdf3bd21,0xbcc8bdfb,0xbddcbd84,0x3d933dd1,0x3dfe3c7b,0x3d443ded,0x3df13d2c,0xbdb9bdb1,0xbdff3c17,0xbd8ebdd5,0xbdfdbc96,0x3dd83d89,0x3df7bd09,
0x3df53d15,0x3d983dce,0xbd21bdf3,0xbdd1bd93,0x3d8ebdd5,0xbbc9be00,0xbd093df7,0x3d383def,0xbded3d44,0xbd843ddc,0x3dc2bda7,0x3ce0bdfa,0x3dfb3cc8,0x3de7bd5b,0xbdfe3c7b,0xbdb93db1,
0x3dc63da2,0x3d5b3de7,0xbce0bdfa,0xbd9dbdca,0x3dfbbcc8,0x3dcebd98,0xbdea3d4f,0xbda73dc2,0xbd44bded,0xbdbebdac,0x3d933dd1,0x3ddf3d7c,0xbdd53d8e,0xbd843ddc,0x3db1bdb9,0x3d21bdf3,
0x3d713de2,0x3cf93df8,0xbc7bbdfe,0xbd38bdef,0x3dd53d8e,0x3df13d2c,0xbde5bd66,0xbdfabce0,0x3dedbd44,0x3dcebd98,0xbddf3d7c,0xbdb93db1,0x3cc8bdfb,0xbbc9be00,0xbc173dff,0x3caf3dfc,
0x3c493dff,0x3bc93e00,0xbb49be00,0xbc17bdff,0x3cc83dfb,0x3cf93df8,0xbce0bdfa,0xbd09bdf7,0x3d443ded,0x3d5b3de7,0xbd4fbdea,0xbd66bde5,0x3d8e3dd5,0x3d983dce,0xbd93bdd1,0xbd9dbdca,
0xbdb53d80,0xbd98bdce,0xbda7bdc2,0xbd89bdd8,0xbdc63da2,0xbbc9be00,0xbc7bbdfe,0x3b49be00,0xbdff3c49,0x3d84bddc,0x3d66bde5,0x3d93bdd1,0xbde2bd71,0x3de7bd5b,0x3ddfbd7c,0x3defbd38,
0x3db53d80,0x3d5b3de7,0x3d933dd1,0x3d093df7,0xbde2bd71,0xbdce3d98,0xbdb13db9,0xbde53d66,0x3d15bdf5,0xbdbebdac,0xbdd8bd89,0xbd9dbdca,0x3dff3c49,0x3d84bddc,0x3d38bdef,0x3da7bdc2,
0xbdb53d80,0xbcf9bdf8,0xbd7cbddf,0x3b49be00,0x3c49bdff,0x3df13d2c,0x3dff3c17,0x3dd13d93,0x3dc63da2,0xbdce3d98,0xbd9d3dca,0xbdef3d38,0xbdf53d15,0xbbc9be00,0xbd21bdf3,0x3ce0bdfa,
0x3db53d80,0x3bc93e00,0x3d4f3dea,0xbd213df3,0x3df5bd15,0xbcf9bdf8,0xbd93bdd1,0x3c7bbdfe,0xbde23d71,0x3d5b3de7,0x3db93db1,0x3c173dff,0x3dc6bda2,0xbd98bdce,0xbdd8bd89,0xbd09bdf7,
0xbdb53d80,0x3c96bdfd,0xbd21bdf3,0x3d93bdd1,0x3da23dc6,0xbdac3dbe,0xbd093df7,0xbdef3d38,0xbc49bdff,0x3df8bcf9,0x3dc2bda7,0x3dfa3ce0,0xbd713de2,0xbdf1bd2c,0xbdfe3c7b,0xbdb1bdb9,
0x3db53d80,0xbd2c3df1,0x3ce03dfa,0xbdca3d9d,0xbd713de2,0x3dfd3c96,0x3deabd4f,0x3dc23da7,0x3df53d15,0xbbc9be00,0xbd93bdd1,0x3d7cbddf,0x3c49bdff,0xbdf83cf9,0xbdb13db9,0xbdf3bd21,
0xbdb53d80,0x3d84bddc,0xbc7bbdfe,0x3defbd38,0xbdffbc49,0xbd5bbde7,0xbde5bd66,0x3ce0bdfa,0xbda23dc6,0xbdfdbc96,0xbddf3d7c,0xbdb1bdb9,0x3d153df5,0xbdac3dbe,0xbc173dff,0xbdfc3caf,
0x3db53d80,0xbdac3dbe,0x3b493e00,0xbdff3c17,0xbd15bdf5,0xbd843ddc,0x3ce03dfa,0xbdf73d09,0xbd71bde2,0xbd2c3df1,0x3d4f3dea,0xbde53d66,0xbda2bdc6,0xbc963dfd,0x3d933dd1,0xbdca3d9d,
0xbdb53d80,0x3dcebd98,0x3c17bdff,0x3dfa3ce0,0x3dc6bda2,0x3e00bbc9,0x3d9dbdca,0x3db13db9,0x3dffbc49,0x3ddc3d84,0x3df3bd21,0x3caf3dfc,0x3de23d71,0x3d5b3de7,0x3df73d09,0xbd4f3dea,
0x3db53d80,0xbde73d5b,0xbcaf3dfc,0xbddfbd7c,0x3de23d71,0xbd98bdce,0xbe003b49,0x3d21bdf3,0xbd153df5,0x3dacbdbe,0xbce0bdfa,0x3dfe3c7b,0xbdffbc49,0x3ddc3d84,0x3deabd4f,0x3c173dff,
0xbdb53d80,0x3df8bcf9,0x3d09bdf7,0x3db13db9,0xbc493dff,0xbd2c3df1,0x3da73dc2,0xbdfc3caf,0xbdc6bda2,0xbd98bdce,0xbdfe3c7b,0x3d4fbdea,0x3df5bd15,0x3e00bbc9,0x3d66bde5,0x3d893dd8,
0x3db53d80,0xbe003bc9,0xbd383def,0xbd66bde5,0xbdf53d15,0x3df8bcf9,0x3cafbdfc,0x3d9d3dca,0x3de2bd71,0xbde73d5b,0x3b493e00,0xbdc2bda7,0xbdc63da2,0x3dcebd98,0xbce0bdfa,0x3ddf3d7c,
0xbdb53d80,0x3dfd3c96,0x3d66bde5,0x3caf3dfc,0xbda2bdc6,0xbdbebdac,0xbddf3d7c,0x3d4fbdea,0x3c493dff,0x3cf93df8,0x3dff3c17,0xbdd83d89,0x3d71bde2,0x3d2cbdf1,0xbdcabd9d,0x3e003b49,
0x3db53d80,0xbdf1bd2c,0xbd893dd8,0x3c7bbdfe,0x3d71bde2,0xbc963dfd,0x3def3d38,0xbdff3c17,0xbdf5bd15,0x3e00bbc9,0x3cafbdfc,0x3d093df7,0xbc493dff,0xbcf9bdf8,0xbe003b49,0x3de5bd66,
0xbdb53d80,0x3ddc3d84,0x3d9dbdca,0xbd4f3dea,0x3dff3c49,0x3de7bd5b,0xbd21bdf3,0x3d893dd8,0x3da2bdc6,0x3c96bdfd,0xbdf7bd09,0x3e003b49,0xbd15bdf5,0xbdbebdac,0xbdc23da7,0x3d93bdd1,
0x3db53d80,0xbdbebdac,0xbdb13db9,0x3da7bdc2,0x3d153df5,0xbddcbd84,0xbd893dd8,0x3d7cbddf,0x3d713de2,0xbdf1bd2c,0xbd383def,0x3d21bdf3,0x3da23dc6,0xbdfdbc96,0xbcaf3dfc,0x3c7bbdfe,
0xbdb53d80,0x3d983dce,0x3dc2bda7,0xbdd83d89,0xbdc63da2,0x3bc93e00,0x3dfebc7b,0xbe00bb49,0xbdff3c49,0xbd843ddc,0x3de53d66,0xbdd1bd93,0xbde2bd71,0xbde73d5b,0x3d7c3ddf,0xbd38bdef,
0x3db53d80,0xbd5bbde7,0xbdd13d93,0x3df7bd09,0xbde2bd71,0x3dcebd98,0xbdb9bdb1,0x3d663de5,0x3d15bdf5,0x3dbe3dac,0x3d89bdd8,0xbdca3d9d,0x3dff3c49,0xbd843ddc,0x3def3d38,0xbdc2bda7,
0xbdb53d80,0x3cf93df8,0x3ddfbd7c,0xbe00bb49,0x3c49bdff,0xbdf1bd2c,0xbc173dff,0x3d93bdd1,0x3dc63da2,0x3dcebd98,0xbdcabd9d,0x3d383def,0xbdf53d15,0x3bc93e00,0x3df3bd21,0xbdfabce0,
0x3db53d80,0xbbc9be00,0xbdea3d4f,0x3df33d21,0x3df5bd15,0x3cf93df8,0x3dd1bd93,0xbdfebc7b,0xbde23d71,0xbd5bbde7,0xbdb13db9,0x3dffbc17,0x3dc6bda2,0x3d983dce,0x3d89bdd8,0xbdf73d09,
0xbdb53d80,0xbc963dfd,0x3df3bd21,0xbdd1bd93,0x3da23dc6,0x3dacbdbe,0xbdf7bd09,0x3d383def,0xbc49bdff,0xbdf83cf9,0x3da73dc2,0x3ce0bdfa,0xbd713de2,0x3df13d2c,0xbc7bbdfe,0xbdb93db1,
0x3db53d80,0x3d2cbdf1,0xbdfa3ce0,0x3d9d3dca,0xbd713de2,0xbdfdbc96,0x3d4f3dea,0x3da7bdc2,0x3df53d15,0x3bc93e00,0x3dd1bd93,0xbddfbd7c,0x3c49bdff,0x3df8bcf9,0xbdb9bdb1,0xbd213df3,
0xbdb53d80,0xbd843ddc,0x3dfebc7b,0xbd38bdef,0xbdffbc49,0x3d5b3de7,0x3d66bde5,0xbdfabce0,0xbda23dc6,0x3dfd3c96,0xbd7cbddf,0xbdb93db1,0x3d153df5,0x3dacbdbe,0xbdffbc17,0x3caf3dfc,
0x3db53d80,0x3dacbdbe,0xbe003b49,0x3c173dff,0xbd15bdf5,0x3d84bddc,0xbdfa3ce0,0x3d093df7,0xbd71bde2,0x3d2cbdf1,0xbdea3d4f,0x3d663de5,0xbda2bdc6,0x3c96bdfd,0xbdd13d93,0x3d9d3dca,
0xbdb53d80,0xbdce3d98,0x3dff3c17,0x3ce0bdfa,0x3dc6bda2,0xbe003bc9,0x3dca3d9d,0x3db9bdb1,0x3dffbc49,0xbddcbd84,0x3d213df3,0x3dfcbcaf,0x3de23d71,0xbd5bbde7,0xbd093df7,0x3dea3d4f,
0x3db53d80,0x3de7bd5b,0xbdfcbcaf,0xbd7c3ddf,0x3de23d71,0x3d983dce,0xbb49be00,0xbdf3bd21,0xbd153df5,0xbdac3dbe,0x3dfabce0,0x3c7bbdfe,0xbdffbc49,0xbddcbd84,0x3d4f3dea,0x3dffbc17,
0xbdb53d80,0xbdf83cf9,0x3df73d09,0x3db9bdb1,0xbc493dff,0x3d2cbdf1,0xbdc23da7,0x3caf3dfc,0xbdc6bda2,0x3d983dce,0xbc7bbdfe,0xbdeabd4f,0x3df5bd15,0xbe003bc9,0x3de53d66,0x3dd8bd89,
0x3db53d80,0x3e00bbc9,0xbdefbd38,0xbde53d66,0xbdf53d15,0xbdf83cf9,0x3dfc3caf,0x3dcabd9d,0x3de2bd71,0x3de7bd5b,0xbe003b49,0xbda73dc2,0xbdc63da2,0xbdce3d98,0x3dfabce0,0x3d7cbddf,
0xbdb53d80,0xbdfdbc96,0x3de53d66,0x3dfcbcaf,0xbda2bdc6,0x3dbe3dac,0xbd7cbddf,0xbdeabd4f,0x3c493dff,0xbcf9bdf8,0xbc173dff,0x3d893dd8,0x3d71bde2,0xbd2c3df1,0x3d9dbdca,0x3b49be00,
0x3db53d80,0x3df13d2c,0xbdd8bd89,0xbdfebc7b,0x3d71bde2,0x3c96bdfd,0xbd383def,0x3c173dff,0xbdf5bd15,0xbe003bc9,0x3dfc3caf,0x3df7bd09,0xbc493dff,0x3cf93df8,0xbb49be00,0xbd66bde5,
0xbdb53d80,0xbddcbd84,0x3dca3d9d,0x3dea3d4f,0x3dff3c49,0xbde73d5b,0x3df3bd21,0x3dd8bd89,0x3da2bdc6,0xbc963dfd,0x3d09bdf7,0x3b49be00,0xbd15bdf5,0x3dbe3dac,0xbda7bdc2,0xbdd1bd93,
0x3db53d80,0x3dbe3dac,0xbdb9bdb1,0xbdc2bda7,0x3d153df5,0x3ddc3d84,0xbdd8bd89,0xbddfbd7c,0x3d713de2,0x3df13d2c,0xbdefbd38,0xbdf3bd21,0x3da23dc6,0x3dfd3c96,0xbdfcbcaf,0xbdfebc7b,
0x3f800000,0x0,0x3f800000,0x0,0x3f800000,0x0,0x3f800000,0x0,0x3f800000,0x0,0x3f800000,0x0,0x3f800000,0x0,0x3f800000,0x0,
0x3f800000,0x0,0x3f7ffb11,0xbc490e90,0x3f7fec43,0xbcc90ab0,0x3f7fd397,0xbd16c32c,0x3f7fb10f,0xbd48fb30,0x3f7f84ab,0xbd7b2b74,0x3f7f4e6d,0xbd96a905,0x3f7f0e58,0xbdafb680,
0x3f800000,0x0,0x3f7fec43,0xbcc90ab0,0x3f7fb10f,0xbd48fb30,0x3f7f4e6d,0xbd96a905,0x3f7ec46d,0xbdc8bd36,0x3f7e1324,0xbdfab273,0x3f7d3aac,0xbe164083,0x3f7c3b28,0xbe2f10a2,
0x3f800000,0x0,0x3f7fd397,0xbd16c32c,0x3f7f4e6d,0xbd96a905,0x3f7e70b0,0xbde1bc2e,0x3f7d3aac,0xbe164083,0x3f7baccd,0xbe3b6ecf,0x3f79c79d,0xbe605c13,0x3f778bc5,0xbe827dc0,
0x3f800000,0x0,0x3f7fb10f,0xbd48fb30,0x3f7ec46d,0xbdc8bd36,0x3f7d3aac,0xbe164083,0x3f7b14be,0xbe47c5c2,0x3f7853f8,0xbe78cfcc,0x3f74fa0b,0xbe94a031,0x3f710908,0xbeac7cd4,
0x3f800000,0x0,0x3f7f84ab,0xbd7b2b74,0x3f7e1324,0xbdfab273,0x3f7baccd,0xbe3b6ecf,0x3f7853f8,0xbe78cfcc,0x3f740bdd,0xbe9aa086,0x3f6ed89e,0xbeb8442a,0x3f68bf3c,0xbed53641,
0x3f800000,0x0,0x3f7f4e6d,0xbd96a905,0x3f7d3aac,0xbe164083,0x3f79c79d,0xbe605c13,0x3f74fa0b,0xbe94a031,0x3f6ed89e,0xbeb8442a,0x3f676bd8,0xbedae880,0x3f5ebe05,0xbefc5d27,
0x3f800000,0x0,0x3f7f0e58,0xbdafb680,0x3f7c3b28,0xbe2f10a2,0x3f778bc5,0xbe827dc0,0x3f710908,0xbeac7cd4,0x3f68bf3c,0xbed53641,0x3f5ebe05,0xbefc5d27,0x3f531849,0xbf10d3cd,
0x3f800000,0x0,0x3f7b14be,0xbe47c5c2,0x3f6c835e,0xbec3ef15,0x3f54db31,0xbf0e39da,0x3f3504f3,0xbf3504f3,0x3f0e39da,0xbf54db31,0x3ec3ef15,0xbf6c835e,0x3e47c5c2,0xbf7b14be,
0x3f800000,0x0,0x3f7a7302,0xbe541501,0x3f6a09a7,0xbecf7bca,0x3f4f7a1f,0xbf15f6d9,0x3f2beb4a,0xbf3daef9,0x3f00e7e4,0xbf5d2d53,0x3ea09ae5,0xbf731447,0x3de1bc2e,0xbf7e70b0,
0x3f800000,0x0,0x3f79c79d,0xbe605c13,0x3f676bd8,0xbedae880,0x3f49d112,0xbf1d7fd1,0x3f226799,0xbf45e403,0x3ee63375,0xbf64aa59,0x3e78cfcc,0xbf7853f8,0x3cc90ab0,0xbf7fec43,
0x3f800000,0x0,0x3f791298,0xbe6c9a7f,0x3f64aa59,0xbee63375,0x3f43e200,0xbf24d225,0x3f187fc0,0xbf4d9f02,0x3ec9b953,0xbf6b4b0c,0x3e2f10a2,0xbf7c3b28,0xbd7b2b74,0xbf7f84ab,
0x3f800000,0x0,0x3f7853f8,0xbe78cfcc,0x3f61c598,0xbef15aea,0x3f3daef9,0xbf2beb4a,0x3f0e39da,0xbf54db31,0x3eac7cd4,0xbf710908,0x3dc8bd36,0xbf7ec46d,0xbe164083,0xbf7d3aac,
0x3f800000,0x0,0x3f778bc5,0xbe827dc0,0x3f5ebe05,0xbefc5d27,0x3f373a23,0xbf32c8c9,0x3f039c3d,0xbf5b941a,0x3e8e9a22,0xbf75dec6,0x3cc90ab0,0xbf7fec43,0xbe6c9a7f,0xbf791298,
0x3f800000,0x0,0x3f76ba07,0xbe888e93,0x3f5b941a,0xbf039c3d,0x3f3085bb,0xbf396842,0x3ef15aea,0xbf61c598,0x3e605c13,0xbf79c79d,0xbd48fb30,0xbf7fb10f,0xbea09ae5,0xbf731447,
0x3f800000,0x0,0x3f75dec6,0xbe8e9a22,0x3f584853,0xbf08f59b,0x3f299415,0xbf3fc767,0x3edae880,0xbf676bd8,0x3e22abb6,0xbf7cbfc9,0xbdfab273,0xbf7e1324,0xbec9b953,0xbf6b4b0c,
0x3f800000,0x0,0x3f7ec46d,0xbdc8bd36,0x3f7b14be,0xbe47c5c2,0x3f74fa0b,0xbe94a031,0x3f6c835e,0xbec3ef15,0x3f61c598,0xbef15aea,0x3f54db31,0xbf0e39da,0x3f45e403,0xbf226799,
0x3f800000,0x0,0x3f6b4b0c,0xbec9b953,0x3f3085bb,0xbf396842,0x3eb263ef,0xbf6ff573,0xbd48fb30,0xbf7fb10f,0xbee0924f,0xbf660f88,0xbf41d870,0xbf273656,0xbf740bdd,0xbe9aa086,
0x3f800000,0x0,0x3f6a09a7,0xbecf7bca,0x3f2beb4a,0xbf3daef9,0x3ea09ae5,0xbf731447,0xbdc8bd36,0xbf7ec46d,0xbefc5d27,0xbf5ebe05,0xbf4d9f02,0xbf187fc0,0xbf79c79d,0xbe605c13,
0x3f800000,0x0,0x3f68bf3c,0xbed53641,0x3f273656,0xbf41d870,0x3e8e9a22,0xbf75dec6,0xbe164083,0xbf7d3aac,0xbf0b9a6b,0xbf5695e5,0xbf584853,0xbf08f59b,0xbf7dabcc,0xbe09cf86,
0x3f800000,0x0,0x3f676bd8,0xbedae880,0x3f226799,0xbf45e403,0x3e78cfcc,0xbf7853f8,0xbe47c5c2,0xbf7b14be,0xbf187fc0,0xbf4d9f02,0xbf61c598,0xbef15aea,0xbf7fb10f,0xbd48fb30,
0x3f800000,0x0,0x3f660f88,0xbee0924f,0x3f1d7fd1,0xbf49d112,0x3e541501,0xbf7a7302,0xbe78cfcc,0xbf7853f8,0xbf24d225,0xbf43e200,0xbf6a09a7,0xbecf7bca,0xbf7fd397,0x3d16c32c,
0x3f800000,0x0,0x3f64aa59,0xbee63375,0x3f187fc0,0xbf4d9f02,0x3e2f10a2,0xbf7c3b28,0xbe94a031,0xbf74fa0b,0xbf3085bb,0xbf396842,0xbf710908,0xbeac7cd4,0xbf7e1324,0x3dfab273,
0x3f800000,0x0,0x3f633c5a,0xbeebcbbb,0x3f13682a,0xbf514d3d,0x3e09cf86,0xbf7dabcc,0xbeac7cd4,0xbf710908,0xbf3b8f3b,0xbf2e3bde,0xbf76ba07,0xbe888e93,0xbf7a7302,0x3e541501,
0x3f800000,0x0,0x3f74fa0b,0xbe94a031,0x3f54db31,0xbf0e39da,0x3f226799,0xbf45e403,0x3ec3ef15,0xbf6c835e,0x3dc8bd36,0xbf7ec46d,0xbe47c5c2,0xbf7b14be,0xbef15aea,0xbf61c598,
0x3f800000,0x0,0x3f531849,0xbf10d3cd,0x3eb8442a,0xbf6ed89e,0xbe6c9a7f,0xbf791298,0xbf3daef9,0xbf2beb4a,0xbf7dabcc,0xbe09cf86,0xbf64aa59,0x3ee63375,0xbef6e0cb,0x3f604621,
0x3f800000,0x0,0x3f514d3d,0xbf13682a,0x3eac7cd4,0xbf710908,0xbe888e93,0xbf76ba07,0xbf45e403,0xbf226799,0xbf7f4e6d,0xbd96a905,0xbf5b941a,0x3f039c3d,0xbecf7bca,0x3f6a09a7,
0x3f800000,0x0,0x3f4f7a1f,0xbf15f6d9,0x3ea09ae5,0xbf731447,0xbe9aa086,0xbf740bdd,0xbf4d9f02,0xbf187fc0,0xbf7ffb11,0xbc490e90,0xbf514d3d,0x3f13682a,0xbea68f12,0x3f721352,
0x3f800000,0x0,0x3f4d9f02,0xbf187fc0,0x3e94a031,0xbf74fa0b,0xbeac7cd4,0xbf710908,0xbf54db31,0xbf0e39da,0xbf7fb10f,0x3d48fb30,0xbf45e403,0x3f226799,0xbe78cfcc,0x3f7853f8,
0x3f800000,0x0,0x3f4bbbf8,0xbf1b02c6,0x3e888e93,0xbf76ba07,0xbebe1d4a,0xbf6db293,0xbf5b941a,0xbf039c3d,0xbf7e70b0,0x3de1bc2e,0xbf396842,0x3f3085bb,0xbe22abb6,0x3f7cbfc9,
0x3f800000,0x0,0x3f49d112,0xbf1d7fd1,0x3e78cfcc,0xbf7853f8,0xbecf7bca,0xbf6a09a7,0xbf61c598,0xbef15aea,0xbf7c3b28,0x3e2f10a2,0xbf2beb4a,0x3f3daef9,0xbd96a905,0x3f7f4e6d,
0x3f800000,0x0,0x3f47de65,0xbf1ff6cb,0x3e605c13,0xbf79c79d,0xbee0924f,0xbf660f88,0xbf676bd8,0xbedae880,0xbf791298,0x3e6c9a7f,0xbf1d7fd1,0x3f49d112,0x3c490e90,0x3f7ffb11,
0x3f800000,0x0,0x3f800000,0x0,0x3f800000,0x0,0x3f800000,0x0,0x40000000,0x0,0x3f800000,0x0,0x3f800000,0x0,0x3f800000,0x0,
0x3f800000,0x0,0x3f7ffb11,0xbc490e90,0x3f7fec43,0xbcc90ab0,0x3f7fd397,0xbd16c32c,0x3fffb10f,0xbdc8fb30,0x3f7f84ab,0xbd7b2b74,0x3f7f4e6d,0xbd96a905,0x3f7f0e58,0xbdafb680,
0x3f800000,0x0,0x3f7fec43,0xbcc90ab0,0x3f7fb10f,0xbd48fb30,0x3f7f4e6d,0xbd96a905,0x3ffec46d,0xbe48bd36,0x3f7e1324,0xbdfab273,0x3f7d3aac,0xbe164083,0x3f7c3b28,0xbe2f10a2,
0x3f800000,0x0,0x3f7fd397,0xbd16c32c,0x3f7f4e6d,0xbd96a905,0x3f7e70b0,0xbde1bc2e,0x3ffd3aac,0xbe964083,0x3f7baccd,0xbe3b6ecf,0x3f79c79d,0xbe605c13,0x3f778bc5,0xbe827dc0,
0x3f800000,0x0,0x3f7fb10f,0xbd48fb30,0x3f7ec46d,0xbdc8bd36,0x3f7d3aac,0xbe164083,0x3ffb14be,0xbec7c5c2,0x3f7853f8,0xbe78cfcc,0x3f74fa0b,0xbe94a031,0x3f710908,0xbeac7cd4,
0x3f800000,0x0,0x3f7f84ab,0xbd7b2b74,0x3f7e1324,0xbdfab273,0x3f7baccd,0xbe3b6ecf,0x3ff853f8,0xbef8cfcc,0x3f740bdd,0xbe9aa086,0x3f6ed89e,0xbeb8442a,0x3f68bf3c,0xbed53641,
0x3f800000,0x0,0x3f7f4e6d,0xbd96a905,0x3f7d3aac,0xbe164083,0x3f79c79d,0xbe605c13,0x3ff4fa0b,0xbf14a031,0x3f6ed89e,0xbeb8442a,0x3f676bd8,0xbedae880,0x3f5ebe05,0xbefc5d27,
0x3f800000,0x0,0x3f7f0e58,0xbdafb680,0x3f7c3b28,0xbe2f10a2,0x3f778bc5,0xbe827dc0,0x3ff10908,0xbf2c7cd4,0x3f68bf3c,0xbed53641,0x3f5ebe05,0xbefc5d27,0x3f531849,0xbf10d3cd,
0x3f800000,0x0,0x3f7ec46d,0xbdc8bd36,0x3f7b14be,0xbe47c5c2,0x3f74fa0b,0xbe94a031,0x3fec835e,0xbf43ef15,0x3f61c598,0xbef15aea,0x3f54db31,0xbf0e39da,0x3f45e403,0xbf226799,
0x3f800000,0x0,0x3f7e70b0,0xbde1bc2e,0x3f79c79d,0xbe605c13,0x3f721352,0xbea68f12,0x3fe76bd8,0xbf5ae880,0x3f59f26a,0xbf064b82,0x3f49d112,0xbf1d7fd1,0x3f373a23,0xbf32c8c9,
0x3f800000,0x0,0x3f7e1324,0xbdfab273,0x3f7853f8,0xbe78cfcc,0x3f6ed89e,0xbeb8442a,0x3fe1c598,0xbf715aea,0x3f514d3d,0xbf13682a,0x3f3daef9,0xbf2beb4a,0x3f273656,0xbf41d870,
0x3f800000,0x0,0x3f7dabcc,0xbe09cf86,0x3f76ba07,0xbe888e93,0x3f6b4b0c,0xbec9b953,0x3fdb941a,0xbf839c3d,0x3f47de65,0xbf1ff6cb,0x3f3085bb,0xbf396842,0x3f15f6d9,0xbf4f7a1f,
0x3f800000,0x0,0x3f7d3aac,0xbe164083,0x3f74fa0b,0xbe94a031,0x3f676bd8,0xbedae880,0x3fd4db31,0xbf8e39da,0x3f3daef9,0xbf2beb4a,0x3f226799,0xbf45e403,0x3f039c3d,0xbf5b941a,
0x3f800000,0x0,0x3f7cbfc9,0xbe22abb6,0x3f731447,0xbea09ae5,0x3f633c5a,0xbeebcbbb,0x3fcd9f02,0xbf987fc0,0x3f32c8c9,0xbf373a23,0x3f13682a,0xbf514d3d,0x3ee0924f,0xbf660f88,
0x3f800000,0x0,0x3f7c3b28,0xbe2f10a2,0x3f710908,0xbeac7cd4,0x3f5ebe05,0xbefc5d27,0x3fc5e403,0xbfa26799,0x3f273656,0xbf41d870,0x3f039c3d,0xbf5b941a,0x3eb8442a,0xbf6ed89e,
0x3f800000,0x0,0x3f7baccd,0xbe3b6ecf,0x3f6ed89e,0xbeb8442a,0x3f59f26a,0xbf064b82,0x3fbdaef9,0xbfabeb4a,0x3f1b02c6,0xbf4bbbf8,0x3ee63375,0xbf64aa59,0x3e8e9a22,0xbf75dec6,
0x3f800000,0x0,0x3f7b14be,0xbe47c5c2,0x3f6c835e,0xbec3ef15,0x3f54db31,0xbf0e39da,0x3fb504f3,0xbfb504f3,0x3f0e39da,0xbf54db31,0x3ec3ef15,0xbf6c835e,0x3e47c5c2,0xbf7b14be,
0x3f800000,0x0,0x3f7a7302,0xbe541501,0x3f6a09a7,0xbecf7bca,0x3f4f7a1f,0xbf15f6d9,0x3fabeb4a,0xbfbdaef9,0x3f00e7e4,0xbf5d2d53,0x3ea09ae5,0xbf731447,0x3de1bc2e,0xbf7e70b0,
0x3f800000,0x0,0x3f79c79d,0xbe605c13,0x3f676bd8,0xbedae880,0x3f49d112,0xbf1d7fd1,0x3fa26799,0xbfc5e403,0x3ee63375,0xbf64aa59,0x3e78cfcc,0xbf7853f8,0x3cc90ab0,0xbf7fec43,
0x3f800000,0x0,0x3f791298,0xbe6c9a7f,0x3f64aa59,0xbee63375,0x3f43e200,0xbf24d225,0x3f987fc0,0xbfcd9f02,0x3ec9b953,0xbf6b4b0c,0x3e2f10a2,0xbf7c3b28,0xbd7b2b74,0xbf7f84ab,
0x3f800000,0x0,0x3f7853f8,0xbe78cfcc,0x3f61c598,0xbef15aea,0x3f3daef9,0xbf2beb4a,0x3f8e39da,0xbfd4db31,0x3eac7cd4,0xbf710908,0x3dc8bd36,0xbf7ec46d,0xbe164083,0xbf7d3aac,
0x3f800000,0x0,0x3f778bc5,0xbe827dc0,0x3f5ebe05,0xbefc5d27,0x3f373a23,0xbf32c8c9,0x3f839c3d,0xbfdb941a,0x3e8e9a22,0xbf75dec6,0x3cc90ab0,0xbf7fec43,0xbe6c9a7f,0xbf791298,
0x3f800000,0x0,0x3f76ba07,0xbe888e93,0x3f5b941a,0xbf039c3d,0x3f3085bb,0xbf396842,0x3f715aea,0xbfe1c598,0x3e605c13,0xbf79c79d,0xbd48fb30,0xbf7fb10f,0xbea09ae5,0xbf731447,
0x3f800000,0x0,0x3f75dec6,0xbe8e9a22,0x3f584853,0xbf08f59b,0x3f299415,0xbf3fc767,0x3f5ae880,0xbfe76bd8,0x3e22abb6,0xbf7cbfc9,0xbdfab273,0xbf7e1324,0xbec9b953,0xbf6b4b0c,
0x3f800000,0x0,0x3f74fa0b,0xbe94a031,0x3f54db31,0xbf0e39da,0x3f226799,0xbf45e403,0x3f43ef15,0xbfec835e,0x3dc8bd36,0xbf7ec46d,0xbe47c5c2,0xbf7b14be,0xbef15aea,0xbf61c598,
0x3f800000,0x0,0x3f740bdd,0xbe9aa086,0x3f514d3d,0xbf13682a,0x3f1b02c6,0xbf4bbbf8,0x3f2c7cd4,0xbff10908,0x3d16c32c,0xbf7fd397,0xbe888e93,0xbf76ba07,0xbf0b9a6b,0xbf5695e5,
0x3f800000,0x0,0x3f731447,0xbea09ae5,0x3f4d9f02,0xbf187fc0,0x3f13682a,0xbf514d3d,0x3f14a031,0xbff4fa0b,0xbcc90ab0,0xbf7fec43,0xbeac7cd4,0xbf710908,0xbf1d7fd1,0xbf49d112,
0x3f800000,0x0,0x3f721352,0xbea68f12,0x3f49d112,0xbf1d7fd1,0x3f0b9a6b,0xbf5695e5,0x3ef8cfcc,0xbff853f8,0xbdafb680,0xbf7f0e58,0xbecf7bca,0xbf6a09a7,0xbf2e3bde,0xbf3b8f3b,
0x3f800000,0x0,0x3f710908,0xbeac7cd4,0x3f45e403,0xbf226799,0x3f039c3d,0xbf5b941a,0x3ec7c5c2,0xbffb14be,0xbe164083,0xbf7d3aac,0xbef15aea,0xbf61c598,0xbf3daef9,0xbf2beb4a,
0x3f800000,0x0,0x3f6ff573,0xbeb263ef,0x3f41d870,0xbf273656,0x3ef6e0cb,0xbf604621,0x3e964083,0xbffd3aac,0xbe541501,0xbf7a7302,0xbf08f59b,0xbf584853,0xbf4bbbf8,0xbf1b02c6,
0x3f800000,0x0,0x3f6ed89e,0xbeb8442a,0x3f3daef9,0xbf2beb4a,0x3ee63375,0xbf64aa59,0x3e48bd36,0xbffec46d,0xbe888e93,0xbf76ba07,0xbf187fc0,0xbf4d9f02,0xbf584853,0xbf08f59b,
0x3f800000,0x0,0x3f6db293,0xbebe1d4a,0x3f396842,0xbf3085bb,0x3ed53641,0xbf68bf3c,0x3dc8fb30,0xbfffb10f,0xbea68f12,0xbf721352,0xbf273656,0xbf41d870,0xbf633c5a,0xbeebcbbb,
0x3f800000,0x0,0x3f7fffb1,0xbb490fc6,0x3f7ffec4,0xbbc90f88,0x3f7ffd39,0xbc16cb58,0x3ffffb11,0xbcc90e90,0x3f7ff84a,0xbc7b514b,0x3f7ff4e6,0xbc96c9b6,0x3f7ff0e3,0xbcafea69,
0x3f800000,0x0,0x3f7ff84a,0xbc7b514b,0x3f7fe129,0xbcfb49ba,0x3f7fba9e,0xbd3c6dd5,0x3fff84ab,0xbdfb2b74,0x3f7f3f54,0xbd9cecf9,0x3f7eea9d,0xbdbc3ac3,0x3f7e868b,0xbddb7d37,
0x3f800000,0x0,0x3f7fe705,0xbce22a7a,0x3f7f9c18,0xbd621469,0x3f7f1f49,0xbda973ba,0x3ffe70b0,0xbe61bc2e,0x3f7d906e,0xbe0cec4a,0x3f7c7eb0,0xbe28defc,0x3f7b3bab,0xbe44b0b9,
0x3f800000,0x0,0x3f7fcbe2,0xbd2351cb,0x3f7f2f9d,0xbda3308c,0x3f7e2b72,0xbdf475c0,0x3ffcbfc9,0xbea2abb6,0x3f7aed37,0xbe4ada4f,0x3f78b47b,0xbe72b651,0x3f76167a,0xbe8d17c0,
0x3f800000,0x0,0x3f7fa6e3,0xbd55880e,0x3f7e9bc9,0xbdd53db9,0x3f7cdf6c,0xbe1f917b,0x3ffa7302,0xbed41501,0x3f77583a,0xbe840270,0x3f73913f,0xbe9d9e78,0x3f6f20b0,0xbeb6ccc3,
0x3f800000,0x0,0x3f7f7808,0xbd83db0a,0x3f7de0b1,0xbe039502,0x3f7b3bab,0xbe44b0b9,0x3ff78bc5,0xbf027dc0,0x3f72d4eb,0xbea21887,0x3f6d1c1d,0xbec1071e,0x3f666771,0xbedf28a9,
0x3f800000,0x0,0x3f7f3f54,0xbd9cecf9,0x3f7cfe73,0xbe1c76de,0x3f7940c0,0xbe698bba,0x3ff40bdd,0xbf1aa086,0x3f6d67a1,0xbebf926f,0x3f655e0b,0xbee363fa,0x3f5bfb34,0xbf02ef9f,
0x3f800000,0x0,0x3f7efcc9,0xbdb5f8da,0x3f7bf531,0xbe354098,0x3f76ef5b,0xbe870ada,0x3feff573,0xbf3263ef,0x3f671599,0xbedc53c1,0x3f5c61c7,0xbf0242b1,0x3f4fefa8,0xbf1553b7,
0x3f800000,0x0,0x3f7eb069,0xbdcefdb7,0x3f7ac516,0xbe4dee60,0x3f74484b,0xbe9920fe,0x3feb4b0c,0xbf49b953,0x3f5fe4e9,0xbef840c8,0x3f5233c6,0xbf121eb0,0x3f425b89,0xbf269de3,
0x3f800000,0x0,0x3f7e5a38,0xbde7fa9a,0x3f796e4e,0xbe667c66,0x3f714c7a,0xbeab0201,0x3fe60f88,0xbf60924f,0x3f57dc7f,0xbf099f4e,0x3f46e22a,0xbf212ff9,0x3f33587a,0xbf36ad7f,
0x3f800000,0x0,0x3f7dfa38,0xbe007745,0x3f77f110,0xbe7ee6e1,0x3f6dfcf2,0xbebca7af,0x3fe04621,0xbf76e0cb,0x3f4f0417,0xbf16999f,0x3f3a7ca4,0xbf2f61a5,0x3f2302d3,0xbf456439,
0x3f800000,0x0,0x3f7d906e,0xbe0cec4a,0x3f764d97,0xbe8b9507,0x3f6a5ad9,0xbece0bea,0x3fd9f26a,0xbf864b82,0x3f456439,0xbf2302d3,0x3f2d1469,0xbf3ca003,0x3f11796b,0xbf52a649,
0x3f800000,0x0,0x3f7d1cdd,0xbe195be0,0x3f748422,0xbe97a117,0x3f666771,0xbedf28a9,0x3fd31849,0xbf90d3cd,0x3f3b0629,0xbf2ecef7,0x3f1ebc12,0xbf48d8b3,0x3efdbabb,0xbf5e5aa6,
0x3f800000,0x0,0x3f7c9f8a,0xbe25c58c,0x3f7294f8,0xbea395c5,0x3f62241a,0xbeeff7fb,0x3fcbbbf8,0xbf9b02c6,0x3f2ff3e6,0xbf39f2ac,0x3f0f8784,0xbf53fac3,0x3ed6a399,0xbf686b39,
0x3f800000,0x0,0x3f7c187a,0xbe3228d4,0x3f708066,0xbeaf713a,0x3f5d924d,0xbf003a06,0x3fc3e200,0xbfa4d225,0x3f24381a,0xbf446337,0x3eff17b2,0xbf5df6be,0x3eadf73c,0xbf70c501,
0x3f800000,0x0,0x3f7b87b2,0xbe3e853e,0x3f6e46be,0xbebb31a0,0x3f58b3a1,0xbf084b92,0x3fbb8f3b,0xbfae3bde,0x3f17de12,0xbf4e1689,0x3eddbe79,0xbf66becc,0x3e840270,0xbf77583a,
0x3f800000,0x0,0x3f7aed37,0xbe4ada4f,0x3f6be858,0xbec6d529,0x3f5389c7,0xbf102dd5,0x3fb2c8c9,0xbfb73a23,0x3f0af1b7,0xbf570348,0x3ebb31a0,0xbf6e46be,0x3e3228d4,0xbf7c187a,
0x3f800000,0x0,0x3f7a4910,0xbe57278f,0x3f696591,0xbed25a09,0x3f4e1689,0xbf17de12,0x3fa99415,0xbfbfc767,0x3efafef7,0xbf5f20db,0x3e97a117,0xbf748422,0x3db5f8da,0xbf7efcc9,
0x3f800000,0x0,0x3f799b43,0xbe636c83,0x3f66becc,0xbeddbe79,0x3f485bca,0xbf1f599f,0x3f9ff6cb,0xbfc7de65,0x3edf28a9,0xbf666771,0x3e667c66,0xbf796e4e,0x3b490fc6,0xbf7fffb1,
0x3f800000,0x0,0x3f78e3d6,0xbe6fa8b2,0x3f63f473,0xbee900b7,0x3f425b89,0xbf269de3,0x3f95f6d9,0xbfcf7a1f,0x3ec27b55,0xbf6cd007,0x3e1c76de,0xbf7cfe73,0xbda973ba,0xbf7f1f49,
0x3f800000,0x0,0x3f7822d1,0xbe7bdba4,0x3f6106f2,0xbef41f07,0x3f3c17d9,0xbf2da859,0x3f8b9a6b,0xbfd695e5,0x3ea5129f,0xbf725470,0x3da3308c,0xbf7f2f9d,0xbe2bf804,0xbf7c5d3a,
0x3f800000,0x0,0x3f77583a,0xbe840270,0x3f5df6be,0xbeff17b2,0x3f3592e7,0xbf34768f,0x3f80e7e4,0xbfdd2d53,0x3e870ada,0xbf76ef5b,0x3bc90f88,0xbf7ffec4,0xbe80f8c0,0xbf77beb7,
0x3f800000,0x0,0x3f76841b,0xbe8a11f7,0x3f5ac450,0xbf04f484,0x3f2ecef7,0xbf3b0629,0x3f6bcbbb,0xbfe33c5a,0x3e5101f1,0xbf7a9c59,0xbd8a200a,0xbf7f6ac7,0xbeab0201,0xbf714c7a,
0x3f800000,0x0,0x3f75a67b,0xbe901c2c,0x3f577026,0xbf0a48ad,0x3f27ce61,0xbf4154e1,0x3f553641,0xbfe8bf3c,0x3e1324ca,0xbf7d57de,0xbe1008b7,0xbf7d7474,0xbed3c867,0xbf6912ae,
0x3f800000,0x0,0x3f74bf62,0xbe9620d2,0x3f53fac3,0xbf0f8784,0x3f209393,0xbf476085,0x3f3e1d4a,0xbfedb293,0x3da973ba,0xbf7f1f49,0xbe5a3997,0xbf7a1e84,0xbefafef7,0xbf5f20db,
0x3f800000,0x0,0x3f73ced9,0xbe9c1faf,0x3f5064af,0xbf14b039,0x3f19210f,0xbf4d26fd,0x3f268f12,0xbff21352,0x3cafea69,0xbf7ff0e3,0xbe919ddd,0xbf756d97,0xbf102dd5,0xbf5389c7,
0x3f800000,0x0,0x3f72d4eb,0xbea21887,0x3f4cae79,0xbf19c200,0x3f11796b,0xbf52a649,0x3f0e9a22,0xbff5dec6,0xbd2351cb,0xbf7fcbe2,0xbeb554ec,0xbf6f6830,0xbf21cbfb,0xbf466354,
0x3f800000,0x0,0x3f71d19f,0xbea80b1f,0x3f48d8b3,0xbf1ebc12,0x3f099f4e,0xbf57dc7f,0x3eec9a7f,0xbff91298,0xbdcefdb7,0xbf7eb069,0xbed8106b,0xbf6816a8,0xbf3238aa,0xbf37c655,
0x3f800000,0x0,0x3f70c501,0xbeadf73c,0x3f44e3f5,0xbf239da9,0x3f019573,0xbf5cc7d1,0x3ebb6ecf,0xbffbaccd,0xbe25c58c,0xbf7c9f8a,0xbef9a02d,0xbf5f8327,0xbf4154e1,0xbf27ce61,
0x3f800000,0x0,0x3f6faf1b,0xbeb3dca5,0x3f40d0da,0xbf286605,0x3ef2bd43,0xbf61668a,0x3e89cf86,0xbffdabcc,0xbe636c83,0xbf799b43,0xbf0cead0,0xbf55b993,0xbf4f0417,0xbf16999f,
0x3f800000,0x0,0x3f6e8ff8,0xbeb9bb1e,0x3f3ca003,0xbf2d1469,0x3ee1fb6a,0xbf65b710,0x3e2fb680,0xbfff0e58,0xbe901c2c,0xbf75a67b,0xbf1c420c,0xbf4ac77f,0xbf5b2c79,0xbf044889,
0x3f800000,0x0,0x3f6d67a1,0xbebf926f,0x3f385216,0xbf31a81d,0x3ed0eb2a,0xbf69b7e4,0x3d96c32c,0xbfffd397,0xbeadf73c,0xbf70c501,0xbf2ac082,0xbf3ebc1b,0xbf65b710,0xbee1fb6a,
0x3f800000,0x0,0x3f7ffec4,0xbbc90f88,0x3f7ffb11,0xbc490e90,0x3f7ff4e6,0xbc96c9b6,0x3fffec43,0xbd490ab0,0x3f7fe129,0xbcfb49ba,0x3f7fd397,0xbd16c32c,0x3f7fc38f,0xbd2fe007,
0x3f800000,0x0,0x3f7ff4e6,0xbc96c9b6,0x3f7fd397,0xbd16c32c,0x3f7f9c18,0xbd621469,0x3fff4e6d,0xbe16a905,0x3f7eea9d,0xbdbc3ac3,0x3f7e70b0,0xbde1bc2e,0x3f7de0b1,0xbe039502,
0x3f800000,0x0,0x3f7fe129,0xbcfb49ba,0x3f7f84ab,0xbd7b2b74,0x3f7eea9d,0xbdbc3ac3,0x3ffe1324,0xbe7ab273,0x3f7cfe73,0xbe1c76de,0x3f7baccd,0xbe3b6ecf,0x3f7a1e84,0xbe5a3997,
0x3f800000,0x0,0x3f7fc38f,0xbd2fe007,0x3f7f0e58,0xbdafb680,0x3f7de0b1,0xbe039502,0x3ffc3b28,0xbeaf10a2,0x3f7a1e84,0xbe5a3997,0x3f778bc5,0xbe827dc0,0x3f748422,0xbe97a117,
0x3f800000,0x0,0x3f7f9c18,0xbd621469,0x3f7e70b0,0xbde1bc2e,0x3f7c7eb0,0xbe28defc,0x3ff9c79d,0xbee05c13,0x3f764d97,0xbe8b9507,0x3f721352,0xbea68f12,0x3f6d1c1d,0xbec1071e,
0x3f800000,0x0,0x3f7f6ac7,0xbd8a200a,0x3f7dabcc,0xbe09cf86,0x3f7ac516,0xbe4dee60,0x3ff6ba07,0xbf088e93,0x3f718f57,0xbea986c4,0x3f6b4b0c,0xbec9b953,0x3f63f473,0xbee900b7,
0x3f800000,0x0,0x3f7f2f9d,0xbda3308c,0x3f7cbfc9,0xbe22abb6,0x3f78b47b,0xbe72b651,0x3ff31447,0xbf209ae5,0x3f6be858,0xbec6d529,0x3f633c5a,0xbeebcbbb,0x3f591e6a,0xbf07a136,
0x3f800000,0x0,0x3f7eea9d,0xbdbc3ac3,0x3f7baccd,0xbe3b6ecf,0x3f764d97,0xbe8b9507,0x3feed89e,0xbf38442a,0x3f655e0b,0xbee363fa,0x3f59f26a,0xbf064b82,0x3f4cae79,0xbf19c200,
0x3f800000,0x0,0x3f7e9bc9,0xbdd53db9,0x3f7a7302,0xbe541501,0x3f73913f,0xbe9d9e78,0x3fea09a7,0xbf4f7bca,0x3f5df6be,0xbeff17b2,0x3f4f7a1f,0xbf15f6d9,0x3f3ebc1b,0xbf2ac082,
0x3f800000,0x0,0x3f7e4323,0xbdee3876,0x3f791298,0xbe6c9a7f,0x3f708066,0xbeaf713a,0x3fe4aa59,0xbf663375,0x3f55b993,0xbf0cead0,0x3f43e200,0xbf24d225,0x3f2f61a5,0xbf3a7ca4,
0x3f800000,0x0,0x3f7de0b1,0xbe039502,0x3f778bc5,0xbe827dc0,0x3f6d1c1d,0xbec1071e,0x3fdebe05,0xbf7c5d27,0x3f4cae79,0xbf19c200,0x3f373a23,0xbf32c8c9,0x3f1ebc12,0xbf48d8b3,
0x3f800000,0x0,0x3f7d7474,0xbe1008b7,0x3f75dec6,0xbe8e9a22,0x3f696591,0xbed25a09,0x3fd84853,0xbf88f59b,0x3f42de29,0xbf26050a,0x3f299415,0xbf3fc767,0x3f0cead0,0xbf55b993,
0x3f800000,0x0,0x3f7cfe73,0xbe1c76de,0x3f740bdd,0xbe9aa086,0x3f655e0b,0xbee363fa,0x3fd14d3d,0xbf93682a,0x3f385216,0xbf31a81d,0x3f1b02c6,0xbf4bbbf8,0x3ef41f07,0xbf6106f2,
0x3f800000,0x0,0x3f7c7eb0,0xbe28defc,0x3f721352,0xbea68f12,0x3f6106f2,0xbef41f07,0x3fc9d112,0xbf9d7fd1,0x3f2d1469,0xbf3ca003,0x3f0b9a6b,0xbf5695e5,0x3ecc9b8b,0xbf6aab7b,
0x3f800000,0x0,0x3f7bf531,0xbe354098,0x3f6ff573,0xbeb263ef,0x3f5c61c7,0xbf0242b1,0x3fc1d870,0xbfa73656,0x3f212ff9,0xbf46e22a,0x3ef6e0cb,0xbf604621,0x3ea395c5,0xbf7294f8,
0x3f800000,0x0,0x3f7b61fc,0xbe419b37,0x3f6db293,0xbebe1d4a,0x3f577026,0xbf0a48ad,0x3fb96842,0xbfb085bb,0x3f14b039,0xbf5064af,0x3ed53641,0xbf68bf3c,0x3e72b651,0xbf78b47b,
0x3f800000,0x0,0x3f7ac516,0xbe4dee60,0x3f6b4b0c,0xbec9b953,0x3f5233c6,0xbf121eb0,0x3fb085bb,0xbfb96842,0x3f07a136,0xbf591e6a,0x3eb263ef,0xbf6ff573,0x3e1c76de,0xbf7cfe73,
0x3f800000,0x0,0x3f7a1e84,0xbe5a3997,0x3f68bf3c,0xbed53641,0x3f4cae79,0xbf19c200,0x3fa73656,0xbfc1d870,0x3ef41f07,0xbf6106f2,0x3e8e9a22,0xbf75dec6,0x3d8a200a,0xbf7f6ac7,
0x3f800000,0x0,0x3f796e4e,0xbe667c66,0x3f660f88,0xbee0924f,0x3f46e22a,0xbf212ff9,0x3f9d7fd1,0xbfc9d112,0x3ed8106b,0xbf6816a8,0x3e541501,0xbf7a7302,0xbc96c9b6,0xbf7ff4e6,
0x3f800000,0x0,0x3f78b47b,0xbe72b651,0x3f633c5a,0xbeebcbbb,0x3f40d0da,0xbf286605,0x3f93682a,0xbfd14d3d,0x3ebb31a0,0xbf6e46be,0x3e09cf86,0xbf7dabcc,0xbdd53db9,0xbf7e9bc9,
0x3f800000,0x0,0x3f77f110,0xbe7ee6e1,0x3f604621,0xbef6e0cb,0x3f3a7ca4,0xbf2f61a5,0x3f88f59b,0xbfd84853,0x3e9d9e78,0xbf73913f,0x3d7b2b74,0xbf7f84ab,0xbe419b37,0xbf7b61fc,
0x3f800000,0x0,0x3f772417,0xbe8586ce,0x3f5d2d53,0xbf00e7e4,0x3f33e7bc,0xbf36206c,0x3f7c5d27,0xbfdebe05,0x3e7ee6e1,0xbf77f110,0xbc490e90,0xbf7ffb11,0xbe8b9507,0xbf764d97,
0x3f800000,0x0,0x3f764d97,0xbe8b9507,0x3f59f26a,0xbf064b82,0x3f2d1469,0xbf3ca003,0x3f663375,0xbfe4aa59,0x3e419b37,0xbf7b61fc,0xbdafb680,0xbf7f0e58,0xbeb554ec,0xbf6f6830,
0x3f800000,0x0,0x3f756d97,0xbe919ddd,0x3f5695e5,0xbf0b9a6b,0x3f26050a,0xbf42de29,0x3f4f7bca,0xbfea09a7,0x3e039502,0xbf7de0b1,0xbe22abb6,0xbf7cbfc9,0xbeddbe79,0xbf66becc,
0x3f800000,0x0,0x3f748422,0xbe97a117,0x3f531849,0xbf10d3cd,0x3f1ebc12,0xbf48d8b3,0x3f38442a,0xbfeed89e,0x3d8a200a,0xbf7f6ac7,0xbe6c9a7f,0xbf791298,0xbf0242b1,0xbf5c61c7,
0x3f800000,0x0,0x3f73913f,0xbe9d9e78,0x3f4f7a1f,0xbf15f6d9,0x3f173c07,0xbf4e8d90,0x3f209ae5,0xbff31447,0x3bc90f88,0xbf7ffec4,0xbe9aa086,0xbf740bdd,0xbf14b039,0xbf5064af,
0x3f800000,0x0,0x3f7294f8,0xbea395c5,0x3f4bbbf8,0xbf1b02c6,0x3f0f8784,0xbf53fac3,0x3f088e93,0xbff6ba07,0xbd621469,0xbf7f9c18,0xbebe1d4a,0xbf6db293,0xbf26050a,0xbf42de29,
0x3f800000,0x0,0x3f718f57,0xbea986c4,0x3f47de65,0xbf1ff6cb,0x3f07a136,0xbf591e6a,0x3ee05c13,0xbff9c79d,0xbdee3876,0xbf7e4323,0xbee0924f,0xbf660f88,0xbf36206c,0xbf33e7bc,
0x3f800000,0x0,0x3f708066,0xbeaf713a,0x3f43e200,0xbf24d225,0x3eff17b2,0xbf5df6be,0x3eaf10a2,0xbffc3b28,0xbe354098,0xbf7bf531,0xbf00e7e4,0xbf5d2d53,0xbf44e3f5,0xbf239da9,
0x3f800000,0x0,0x3f6f6830,0xbeb554ec,0x3f3fc767,0xbf299415,0x3eee9479,0xbf628210,0x3e7ab273,0xbffe1324,0xbe72b651,0xbf78b47b,0xbf10d3cd,0xbf531849,0xbf5233c6,0xbf121eb0,
0x3f800000,0x0,0x3f6e46be,0xbebb31a0,0x3f3b8f3b,0xbf2e3bde,0x3eddbe79,0xbf66becc,0x3e16a905,0xbfff4e6d,0xbe97a117,0xbf748422,0xbf1ff6cb,0xbf47de65,0xbf5df6be,0xbeff17b2,
0x3f800000,0x0,0x3f6d1c1d,0xbec1071e,0x3f373a23,0xbf32c8c9,0x3ecc9b8b,0xbf6aab7b,0x3d490ab0,0xbfffec43,0xbeb554ec,0xbf6f6830,0xbf2e3bde,0xbf3b8f3b,0xbf6816a8,0xbed8106b,
0x3f800000,0x0,0x3f7ffd39,0xbc16cb58,0x3f7ff4e6,0xbc96c9b6,0x3f7fe705,0xbce22a7a,0x3fffd397,0xbd96c32c,0x3f7fba9e,0xbd3c6dd5,0x3f7f9c18,0xbd621469,0x3f7f7808,0xbd83db0a,
0x3f800000,0x0,0x3f7ff0e3,0xbcafea69,0x3f7fc38f,0xbd2fe007,0x3f7f7808,0xbd83db0a,0x3fff0e58,0xbe2fb680,0x3f7e868b,0xbddb7d37,0x3f7de0b1,0xbe039502,0x3f7d1cdd,0xbe195be0,
0x3f800000,0x0,0x3f7fdaaf,0xbd0a342f,0x3f7f6ac7,0xbd8a200a,0x3f7eb069,0xbdcefdb7,0x3ffdabcc,0xbe89cf86,0x3f7c5d3a,0xbe2bf804,0x3f7ac516,0xbe4dee60,0x3f78e3d6,0xbe6fa8b2,
0x3f800000,0x0,0x3f7fba9e,0xbd3c6dd5,0x3f7eea9d,0xbdbc3ac3,0x3f7d906e,0xbe0cec4a,0x3ffbaccd,0xbebb6ecf,0x3f7940c0,0xbe698bba,0x3f764d97,0xbe8b9507,0x3f72d4eb,0xbea21887,
0x3f800000,0x0,0x3f7f90b1,0xbd6ea038,0x3f7e4323,0xbdee3876,0x3f7c187a,0xbe3228d4,0x3ff91298,0xbeec9a7f,0x3f75341d,0xbe931f35,0x3f708066,0xbeaf713a,0x3f6afb8c,0xbecb2aae,
0x3f800000,0x0,0x3f7f5ce9,0xbd9064b4,0x3f7d7474,0xbe1008b7,0x3f7a4910,0xbe57278f,0x3ff5dec6,0xbf0e9a22,0x3f703b37,0xbeb0eacb,0x3f696591,0xbed25a09,0x3f61668a,0xbef2bd43,
0x3f800000,0x0,0x3f7f1f49,0xbda973ba,0x3f7c7eb0,0xbe28defc,0x3f7822d1,0xbe7bdba4,0x3ff21352,0xbf268f12,0x3f6a5ad9,0xbece0bea,0x3f6106f2,0xbef41f07,0x3f5627fe,0xbf0c42c9,
0x3f800000,0x0,0x3f7ed7d4,0xbdc27c39,0x3f7b61fc,0xbe419b37,0x3f75a67b,0xbe901c2c,0x3fedb293,0xbf3e1d4a,0x3f6398ac,0xbeea6681,0x3f577026,0xbf0a48ad,0x3f495521,0xbf1e1e22,
0x3f800000,0x0,0x3f7e868b,0xbddb7d37,0x3f7a1e84,0xbe5a3997,0x3f72d4eb,0xbea21887,0x3fe8bf3c,0xbf553641,0x3f5bfb34,0xbf02ef9f,0x3f4cae79,0xbf19c200,0x3f3b0629,0xbf2ecef7,
0x3f800000,0x0,0x3f7e2b72,0xbdf475c0,0x3f78b47b,0xbe72b651,0x3f6faf1b,0xbeb3dca5,0x3fe33c5a,0xbf6bcbbb,0x3f5389c7,0xbf102dd5,0x3f40d0da,0xbf286605,0x3f2b561b,0xbf3e35c5,
0x3f800000,0x0,0x3f7dc68c,0xbe06b26e,0x3f772417,0xbe8586ce,0x3f6c3624,0xbec5625c,0x3fdd2d53,0xbf80e7e4,0x3f4a4c87,0xbf1ce11f,0x3f33e7bc,0xbf36206c,0x3f1a6293,0xbf4c3578,
0x3f800000,0x0,0x3f7d57de,0xbe1324ca,0x3f756d97,0xbe919ddd,0x3f686b39,0xbed6a399,0x3fd695e5,0xbf8b9a6b,0x3f404c5c,0xbf28fd41,0x3f26050a,0xbf42de29,0x3f084b92,0xbf58b3a1,
0x3f800000,0x0,0x3f7cdf6c,0xbe1f917b,0x3f73913f,0xbe9d9e78,0x3f644fac,0xbee79a5d,0x3fcf7a1f,0xbf95f6d9,0x3f3592e7,0xbf34768f,0x3f173c07,0xbf4e8d90,0x3eea6681,0xbf6398ac,
0x3f800000,0x0,0x3f7c5d3a,0xbe2bf804,0x3f718f57,0xbea986c4,0x3f5fe4e9,0xbef840c8,0x3fc7de65,0xbf9ff6cb,0x3f2a2a80,0xbf3f41fc,0x3f07a136,0xbf591e6a,0x3ec27b55,0xbf6cd007,
0x3f800000,0x0,0x3f7bd14d,0xbe3857ec,0x3f6f6830,0xbeb554ec,0x3f5b2c79,0xbf044889,0x3fbfc767,0xbfa99415,0x3f1e1e22,0xbf495521,0x3eee9479,0xbf628210,0x3e9920fe,0xbf74484b,
0x3f800000,0x0,0x3f7b3bab,0xbe44b0b9,0x3f6d1c1d,0xbec1071e,0x3f5627fe,0xbf0c42c9,0x3fb73a23,0xbfb2c8c9,0x3f11796b,0xbf52a649,0x3ecc9b8b,0xbf6aab7b,0x3e5d4b1a,0xbf79f35e,
0x3f800000,0x0,0x3f7a9c59,0xbe5101f1,0x3f6aab7b,0xbecc9b8b,0x3f50d937,0xbf140c5f,0x3fae3bde,0xbfbb8f3b,0x3f044889,0xbf5b2c79,0x3ea986c4,0xbf718f57,0x3e06b26e,0xbf7dc68c,
0x3f800000,0x0,0x3f79f35e,0xbe5d4b1a,0x3f6816a8,0xbed8106b,0x3f4b41fa,0xbf1ba299,0x3fa4d225,0xbfc3e200,0x3eed3063,0xbf62df7b,0x3e8586ce,0xbf772417,0x3d3c6dd5,0xbf7fba9e,
0x3f800000,0x0,0x3f7940c0,0xbe698bba,0x3f655e0b,0xbee363fa,0x3f456439,0xbf2302d3,0x3f9b02c6,0xbfcbbbf8,0x3ed0eb2a,0xbf69b7e4,0x3e419b37,0xbf7b61fc,0xbd2351cb,0xbf7fcbe2,
0x3f800000,0x0,0x3f788486,0xbe75c35a,0x3f628210,0xbeee9479,0x3f3f41fc,0xbf2a2a80,0x3f90d3cd,0xbfd31849,0x3eb3dca5,0xbf6faf1b,0x3dee3876,0xbf7e4323,0xbe007745,0xbf7dfa38,
0x3f800000,0x0,0x3f77beb7,0xbe80f8c0,0x3f5f8327,0xbef9a02d,0x3f38dd65,0xbf311722,0x3f864b82,0xbfd9f26a,0x3e9620d2,0xbf74bf62,0x3d2fe007,0xbf7fc38f,0xbe57278f,0xbf7a4910,
0x3f800000,0x0,0x3f76ef5b,0xbe870ada,0x3f5c61c7,0xbf0242b1,0x3f3238aa,0xbf37c655,0x3f76e0cb,0xbfe04621,0x3e6fa8b2,0xbf78e3d6,0xbcfb49ba,0xbf7fe129,0xbe9620d2,0xbf74bf62,
0x3f800000,0x0,0x3f76167a,0xbe8d17c0,0x3f591e6a,0xbf07a136,0x3f2b561b,0xbf3e35c5,0x3f60924f,0xbfe60f88,0x3e3228d4,0xbf7c187a,0xbdd53db9,0xbf7e9bc9,0xbebf926f,0xbf6d67a1,
0x3f800000,0x0,0x3f75341d,0xbe931f35,0x3f55b993,0xbf0cead0,0x3f24381a,0xbf446337,0x3f49b953,0xbfeb4b0c,0x3de7fa9a,0xbf7e5a38,0xbe354098,0xbf7bf531,0xbee79a5d,0xbf644fac,
0x3f800000,0x0,0x3f74484b,0xbe9920fe,0x3f5233c6,0xbf121eb0,0x3f1ce11f,0xbf4a4c87,0x3f3263ef,0xbfeff573,0x3d55880e,0xbf7fa6e3,0xbe7ee6e1,0xbf77f110,0xbf06f686,0xbf5988ad,
0x3f800000,0x0,0x3f73530e,0xbe9f1cdf,0x3f4e8d90,0xbf173c07,0x3f1553b7,0xbf4fefa8,0x3f1aa086,0xbff40bdd,0xbc16cb58,0xbf7ffd39,0xbea395c5,0xbf7294f8,0xbf19210f,0xbf4d26fd,
0x3f800000,0x0,0x3f725470,0xbea5129f,0x3f4ac77f,0xbf1c420c,0x3f0d9281,0xbf554aa4,0x3f027dc0,0xbff78bc5,0xbd9064b4,0xbf7f5ce9,0xbec6d529,0xbf6be858,0xbf2a2a80,0xbf3f41fc,
0x3f800000,0x0,0x3f714c7a,0xbeab0201,0x3f46e22a,0xbf212ff9,0x3f05a02c,0xbf5a5ba0,0x3ed41501,0xbffa7302,0xbe06b26e,0xbf7dc68c,0xbee900b7,0xbf63f473,0xbf39f2ac,0xbf2ff3e6,
0x3f800000,0x0,0x3f703b37,0xbeb0eacb,0x3f42de29,0xbf26050a,0x3efafef7,0xbf5f20db,0x3ea2abb6,0xbffcbfc9,0xbe44b0b9,0xbf7b3bab,0xbf04f484,0xbf5ac450,0xbf485bca,0xbf1f599f,
0x3f800000,0x0,0x3f6f20b0,0xbeb6ccc3,0x3f3ebc1b,0xbf2ac082,0x3eea6681,0xbf6398ac,0x3e61bc2e,0xbffe70b0,0xbe80f8c0,0xbf77beb7,0xbf14b039,0xbf5064af,0xbf554aa4,0xbf0d9281,
0x3f800000,0x0,0x3f6dfcf2,0xbebca7af,0x3f3a7ca4,0xbf2f61a5,0x3ed97cb9,0xbf67c187,0x3dfb2b74,0xbfff84ab,0xbe9f1cdf,0xbf73530e,0xbf239da9,0xbf44e3f5,0xbf60a6cf,0xbef58035,
0x3f800000,0x0,0x3f6cd007,0xbec27b55,0x3f36206c,0xbf33e7bc,0x3ec8477c,0xbf6b99fb,0x3cc90e90,0xbffffb11,0xbebca7af,0xbf6dfcf2,0xbf31a81d,0xbf385216,0xbf6a5ad9,0xbece0bea,
0x3f800000,0x0,0x0,0x0,0x0,0x0,0x0,0x0,0x0,0x0,0x0,0x0,0x0,0x0,0x0,0x0,
0x0,0x0,0x0,0x0,0x0,0x0,0x0,0x0,0x0,0x0,0x0,0x0,0x0,0x0,0x0,0x0,
0x0,0x0,0x3e000000,0xbf20dff7,0x3ed0c429,0x0,0x3e000000,0x3e61f78b,0x3e0a8bd4,0x0,0x3e000000,0x3d5413cd,0x3d5df9ad,0x0,0x3e000000,0x3cf043ab,
0x0,0x0,0x3e000000,0x3ccbafaf,0xbd5df9ad,0x0,0x3e000000,0x3cf043ab,0xbe0a8bd4,0x0,0x3e000000,0x3d5413cd,0xbed0c429,0x0,0x3e000000,0x3e61f78b,
0x0,0x0,0x0,0x0,0x3f000000,0x0,0x0,0x3f000000,0x0,0x0,0x0,0x0,0x0,0x0,0x0,0x0,
0x0,0x0,0x0,0x0,0x0,0x0,0x0,0x0,0x0,0x0,0x0,0x0,0x3f000000,0x0,0x0,0xbf000000,
0x0,0x0,0x3e000000,0xbe3f90c7,0xbe8b7e3f,0x0,0x3e000000,0xbeb641af,0x3ea73d75,0x0,0x3e000000,0x3e9a827a,0x3da61ad1,0x0,0x3e000000,0x3dd906bd,
0x0,0x0,0x3e000000,0x3dab0dc1,0xbda61ad1,0x0,0x3e000000,0x3dd906bd,0xbea73d75,0x0,0x3e000000,0x3e9a827a,0x3e8b7e3f,0x0,0x3e000000,0xbeb641af,
0x0,0x0,0x0,0x0,0x0,0x0,0x0,0x0,0x3f000000,0x0,0x0,0x3f000000,0x0,0x0,0x0,0x0,
0x0,0x0,0x0,0x0,0x0,0x0,0x0,0x0,0x3f000000,0x0,0x0,0xbf000000,0x0,0x0,0x0,0x0,
0x0,0x0,0x3e000000,0xbdab0dc1,0xbda61ad1,0x0,0x3e000000,0xbdd906bd,0xbea73d75,0x0,0x3e000000,0xbe9a827a,0x3e8b7e3f,0x0,0x3e000000,0x3eb641af,
0x0,0x0,0x3e000000,0x3e3f90c7,0xbe8b7e3f,0x0,0x3e000000,0x3eb641af,0x3ea73d75,0x0,0x3e000000,0xbe9a827a,0x3da61ad1,0x0,0x3e000000,0xbdd906bd,
0x0,0x0,0x0,0x0,0x0,0x0,0x0,0x0,0x0,0x0,0x0,0x0,0x3f000000,0x0,0x0,0x3f000000,
0x0,0x0,0x0,0x0,0x3f000000,0x0,0x0,0xbf000000,0x0,0x0,0x0,0x0,0x0,0x0,0x0,0x0,
0x0,0x0,0x3e000000,0xbccbafaf,0xbd5df9ad,0x0,0x3e000000,0xbcf043ab,0xbe0a8bd4,0x0,0x3e000000,0xbd5413cd,0xbed0c429,0x0,0x3e000000,0xbe61f78b,
0x0,0x0,0x3e000000,0x3f20dff7,0x3ed0c429,0x0,0x3e000000,0xbe61f78b,0x3e0a8bd4,0x0,0x3e000000,0xbd5413cd,0x3d5df9ad,0x0,0x3e000000,0xbcf043ab,
};

struct Params {
    const __nv_bfloat16 *wr, *wi, *lre, *lim, *ldt, *dsk;
    float* out;
};

struct cf { float x, y; };
#define YIELD() asm volatile("pmevent 1;")
#define YS 15
#define YIELD_S1() do { if (YS & 1) YIELD(); } while (0)
#define YIELD_S2() do { if (YS & 2) YIELD(); } while (0)
#define YIELD_S3() do { if (YS & 4) YIELD(); } while (0)
__device__ __forceinline__ uint32_t smem_u32(const void* p) { return (uint32_t)__cvta_generic_to_shared(p); }
__device__ __forceinline__ void mbar_init(uint32_t a, uint32_t c) { asm volatile("mbarrier.init.shared::cta.b64 [%0], %1;" ::"r"(a), "r"(c) : "memory"); }
__device__ __forceinline__ void mbar_expect_tx(uint32_t a, uint32_t b) { asm volatile("mbarrier.arrive.expect_tx.shared::cta.b64 _, [%0], %1;" ::"r"(a), "r"(b) : "memory"); }
__device__ __forceinline__ void mbar_arrive(uint32_t a) { asm volatile("mbarrier.arrive.shared::cta.b64 _, [%0];" ::"r"(a) : "memory"); }
__device__ __forceinline__ void warp_arrive(uint32_t a) {
    __syncwarp();
    asm volatile("{.reg .pred p; elect.sync _|p, 0xffffffff; @p mbarrier.arrive.shared::cta.b64 _, [%0];}" ::"r"(a) : "memory");
}
__device__ __forceinline__ uint32_t mbar_try(uint32_t a, uint32_t ph) {
    uint32_t ok;
    asm volatile("{.reg .pred p; mbarrier.try_wait.parity.shared::cta.b64 p, [%1], %2; selp.u32 %0, 1, 0, p;}" : "=r"(ok) : "r"(a), "r"(ph) : "memory");
    return ok;
}
__device__ __forceinline__ void mbar_wait(uint32_t a, uint32_t ph) {
    uint32_t ok, n = 0;
    do { ok = mbar_try(a, ph); } while (!ok && ++n < SPIN_LIMIT);
}
__device__ __forceinline__ void mbar_wait_fast(uint32_t a, uint32_t ph) { if (!mbar_try(a, ph)) mbar_wait(a, ph); }
__device__ __forceinline__ unsigned ld_rlx(const unsigned* p) { unsigned v; asm volatile("ld.relaxed.gpu.global.u32 %0, [%1];" : "=r"(v) : "l"(p) : "memory"); return v; }
__device__ __forceinline__ void wait_cnt(const unsigned* p, unsigned target) {
    unsigned n = 0;
    while ((int)(ld_rlx(p) - target) < 0 && ++n < SPIN_LIMIT) __nanosleep(20);
}
__device__ __forceinline__ void red_hint(unsigned* p) { asm volatile("red.relaxed.gpu.global.add.u32 [%0], 1;" ::"l"(p) : "memory"); }
__device__ __forceinline__ void fence_async() { asm volatile("fence.proxy.async.global;" ::: "memory"); }
__device__ __forceinline__ void fence_async_sm() { asm volatile("fence.proxy.async.shared::cta;" ::: "memory"); }
#define bar_sync(id, n) asm volatile("bar.sync %0, %1;" ::"n"(id), "n"(n) : "memory")
#define bar_arrive(id, n) asm volatile("bar.arrive %0, %1;" ::"n"(id), "n"(n) : "memory")
__device__ __forceinline__ bool elect_one() {
    uint32_t r;
    asm volatile("{.reg .pred p; elect.sync _|p, 0xffffffff; selp.u32 %0, 1, 0, p;}" : "=r"(r));
    return r != 0;
}

__device__ __forceinline__ void tma2d(uint32_t dst, const CUtensorMap* m, int c0, int c1, uint32_t bar) {
    asm volatile("cp.async.bulk.tensor.2d.shared::cluster.global.mbarrier::complete_tx::bytes [%0], [%1, {%3,%4}], [%2];" ::"r"(dst), "l"(m), "r"(bar), "r"(c0), "r"(c1) : "memory");
}
__device__ __forceinline__ void tma3d(uint32_t dst, const CUtensorMap* m, int c0, int c1, int c2, uint32_t bar) {
    asm volatile("cp.async.bulk.tensor.3d.shared::cluster.global.mbarrier::complete_tx::bytes [%0], [%1, {%3,%4,%5}], [%2];" ::"r"(dst), "l"(m), "r"(bar), "r"(c0), "r"(c1), "r"(c2) : "memory");
}
__device__ __forceinline__ void tma2d_mc(uint32_t dst, const CUtensorMap* m, int c0, int c1, uint32_t bar) {
    asm volatile("cp.async.bulk.tensor.2d.shared::cluster.global.mbarrier::complete_tx::bytes.multicast::cluster [%0], [%1, {%3,%4}], [%2], %5;" ::"r"(dst), "l"(m), "r"(bar), "r"(c0), "r"(c1), "h"((uint16_t)3) : "memory");
}
__device__ __forceinline__ void tma4d_mc(uint32_t dst, const CUtensorMap* m, int c0, int c1, int c2, int c3, uint32_t bar) {
    asm volatile("cp.async.bulk.tensor.4d.shared::cluster.global.mbarrier::complete_tx::bytes.multicast::cluster [%0], [%1, {%3,%4,%5,%6}], [%2], %7;" ::"r"(dst), "l"(m), "r"(bar), "r"(c0), "r"(c1), "r"(c2), "r"(c3), "h"((uint16_t)3) : "memory");
}
__device__ __forceinline__ void tma4d(uint32_t dst, const CUtensorMap* m, int c0, int c1, int c2, int c3, uint32_t bar) {
    asm volatile("cp.async.bulk.tensor.4d.shared::cluster.global.mbarrier::complete_tx::bytes [%0], [%1, {%3,%4,%5,%6}], [%2];" ::"r"(dst), "l"(m), "r"(bar), "r"(c0), "r"(c1), "r"(c2), "r"(c3) : "memory");
}
__device__ __forceinline__ void tma2d_st(const CUtensorMap* m, int c0, int c1, uint32_t src) {
    asm volatile("cp.async.bulk.tensor.2d.global.shared::cta.bulk_group [%0, {%2,%3}], [%1];" ::"l"(m), "r"(src), "r"(c0), "r"(c1) : "memory");
}
__device__ __forceinline__ void tma3d_st(const CUtensorMap* m, int c0, int c1, int c2, uint32_t src) {
    asm volatile("cp.async.bulk.tensor.3d.global.shared::cta.bulk_group [%0, {%2,%3,%4}], [%1];" ::"l"(m), "r"(src), "r"(c0), "r"(c1), "r"(c2) : "memory");
}
__device__ __forceinline__ void tma5d(uint32_t dst, const CUtensorMap* m, int c0, int c1, int c2, int c3, int c4, uint32_t bar) {
    asm volatile("cp.async.bulk.tensor.5d.shared::cluster.global.mbarrier::complete_tx::bytes [%0], [%1, {%3,%4,%5,%6,%7}], [%2];" ::"r"(dst), "l"(m), "r"(bar), "r"(c0), "r"(c1), "r"(c2), "r"(c3), "r"(c4) : "memory");
}
__device__ __forceinline__ void tma5d_mc(uint32_t dst, const CUtensorMap* m, int c0, int c1, int c2, int c3, int c4, uint32_t bar) {
    asm volatile("cp.async.bulk.tensor.5d.shared::cluster.global.mbarrier::complete_tx::bytes.multicast::cluster [%0], [%1, {%3,%4,%5,%6,%7}], [%2], %8;" ::"r"(dst), "l"(m), "r"(bar), "r"(c0), "r"(c1), "r"(c2), "r"(c3), "r"(c4), "h"((uint16_t)3) : "memory");
}
__device__ __forceinline__ void bulk_pf(const void* src, uint32_t n) { asm volatile("cp.async.bulk.prefetch.L2.global [%0], %1;" ::"l"(src), "r"(n) : "memory"); }
__device__ __forceinline__ void tma4d_pf(const CUtensorMap* m, int c0, int c1, int c2, int c3) {
    asm volatile("cp.async.bulk.prefetch.tensor.4d.L2.global [%0, {%1,%2,%3,%4}];" ::"l"(m), "r"(c0), "r"(c1), "r"(c2), "r"(c3) : "memory");
}
__device__ __forceinline__ void tma5d_pf(const CUtensorMap* m, int c0, int c1, int c2, int c3, int c4) {
    asm volatile("cp.async.bulk.prefetch.tensor.5d.L2.global [%0, {%1,%2,%3,%4,%5}];" ::"l"(m), "r"(c0), "r"(c1), "r"(c2), "r"(c3), "r"(c4) : "memory");
}
__device__ __forceinline__ void bulk_ld(uint32_t dst, const void* src, uint32_t n, uint32_t bar) {
    asm volatile("cp.async.bulk.shared::cluster.global.mbarrier::complete_tx::bytes [%0], [%1], %2, [%3];" ::"r"(dst), "l"(src), "r"(n), "r"(bar) : "memory");
}
__device__ __forceinline__ void bulk_st(void* dst, uint32_t src, uint32_t n) {
    asm volatile("cp.async.bulk.global.shared::cta.bulk_group [%0], [%1], %2;" ::"l"(dst), "r"(src), "r"(n) : "memory");
}
__device__ __forceinline__ void bulk_commit() { asm volatile("cp.async.bulk.commit_group;" ::: "memory"); }
__device__ __forceinline__ void bulk_wait_read() { asm volatile("cp.async.bulk.wait_group.read 0;" ::: "memory"); }
__device__ __forceinline__ void bulk_wait_all() { asm volatile("cp.async.bulk.wait_group 0;" ::: "memory"); }
__device__ __forceinline__ void stsm4(uint32_t a, uint32_t r0, uint32_t r1, uint32_t r2, uint32_t r3) {
    asm volatile("stmatrix.sync.aligned.m8n8.x4.shared.b16 [%0], {%1,%2,%3,%4};" ::"r"(a), "r"(r0), "r"(r1), "r"(r2), "r"(r3) : "memory");
}
__device__ __forceinline__ void sts128(uint32_t a, uint32_t r0, uint32_t r1, uint32_t r2, uint32_t r3) {
    asm volatile("st.shared.v4.b32 [%0], {%1,%2,%3,%4};" ::"r"(a), "r"(r0), "r"(r1), "r"(r2), "r"(r3) : "memory");
}
__device__ __forceinline__ void lds128f(uint32_t a, float& x, float& y, float& z, float& u) { asm volatile("ld.shared.v4.f32 {%0,%1,%2,%3}, [%4];" : "=f"(x), "=f"(y), "=f"(z), "=f"(u) : "r"(a) : "memory"); }
__device__ __forceinline__ cf lds_cf(uint32_t a) { cf v; asm volatile("ld.shared.v2.f32 {%0,%1}, [%2];" : "=f"(v.x), "=f"(v.y) : "r"(a) : "memory"); return v; }
__device__ __forceinline__ void stg128(const void* a, uint32_t r0, uint32_t r1, uint32_t r2, uint32_t r3) {
    asm volatile("st.global.v4.b32 [%0], {%1,%2,%3,%4};" ::"l"(a), "r"(r0), "r"(r1), "r"(r2), "r"(r3) : "memory");
}
__device__ __forceinline__ int fresh_lane() { int v; asm volatile("mov.u32 %0, %%laneid;" : "=r"(v)); return v; }
__device__ __forceinline__ uint32_t opaque32(uint32_t v) { asm volatile("" : "+r"(v)); return v; }
__device__ __forceinline__ const uint8_t* padd(const void* base, uint32_t off) {
    uint64_t r;
    asm("{.reg .u32 l, h; mov.b64 {l, h}, %1; add.cc.u32 l, l, %2; addc.u32 h, h, 0; mov.b64 %0, {l, h};}" : "=l"(r) : "l"(base), "r"(off));
    return (const uint8_t*)r;
}
template <int N, int STRIDE> __device__ __forceinline__ void ldtab(uint32_t (&v)[4 * N], uint32_t off) {
    const uint8_t* a = padd(g_tab, off);
#pragma unroll
    for (int i = 0; i < N; i++)
        asm volatile("ld.global.nc.v4.b32 {%0,%1,%2,%3}, [%4];" : "=r"(v[4 * i]), "=r"(v[4 * i + 1]), "=r"(v[4 * i + 2]), "=r"(v[4 * i + 3]) : "l"(a + i * STRIDE));
}
template <int STRIDE> __device__ __forceinline__ void ldtab_cf(cf (&t)[8], uint32_t off) {
    uint32_t v[16];
    ldtab<4, STRIDE>(v, off);
#pragma unroll
    for (int i = 0; i < 8; i++) t[i] = {__uint_as_float(v[2 * i]), __uint_as_float(v[2 * i + 1])};
}
__device__ __forceinline__ uint32_t lds16(uint32_t a) { uint32_t v; asm volatile("ld.shared.u16 %0, [%1];" : "=r"(v) : "r"(a)); return v; }
__device__ __forceinline__ unsigned get_epoch(uint32_t bars) {
    mbar_wait(bars + B_EP, 0);
    unsigned e;
    asm volatile("ld.shared.u32 %0, [%1];" : "=r"(e) : "r"(bars + B_EPOCH) : "memory");
    return e;
}
__device__ __forceinline__ void sts64(uint32_t a, uint32_t x, uint32_t y) { asm volatile("st.shared.v2.b32 [%0], {%1,%2};" ::"r"(a), "r"(x), "r"(y) : "memory"); }
__device__ __forceinline__ uint32_t pk(float lo, float hi) { uint32_t r; asm("cvt.rn.bf16x2.f32 %0, %1, %2;" : "=r"(r) : "f"(hi), "f"(lo)); return r; }
__device__ __forceinline__ float bf2f(unsigned short v) { return __uint_as_float((uint32_t)v << 16); }

__device__ __forceinline__ uint64_t mkdesc(uint32_t addr, uint32_t lbo, uint32_t sbo, uint32_t swz) {
    return (uint64_t)((addr & 0x3FFFF) >> 4) | ((uint64_t)(lbo >> 4) << 16) | ((uint64_t)(sbo >> 4) << 32) | ((uint64_t)swz << 62);
}
__device__ __forceinline__ uint64_t opaque(uint64_t v) { asm volatile("" : "+l"(v)); return v; }
__device__ __forceinline__ void wg_fence() { asm volatile("wgmma.fence.sync.aligned;" ::: "memory"); }
__device__ __forceinline__ void wg_commit() { asm volatile("wgmma.commit_group.sync.aligned;" ::: "memory"); }
template <int N> __device__ __forceinline__ void wg_wait() { asm volatile("wgmma.wait_group.sync.aligned %0;" ::"n"(N) : "memory"); }
template <int N> __device__ __forceinline__ void pin(float (&d)[N]) {
#pragma unroll
    for (int i = 0; i < N; i++) asm volatile("" : "+f"(d[i])::"memory");
}
template <int N> __device__ __forceinline__ void pinu(uint32_t (&d)[N]) {
#pragma unroll
    for (int i = 0; i < N; i++) asm volatile("" : "+r"(d[i])::"memory");
}

#define R8(d, o) "+f"(d[o]), "+f"(d[o + 1]), "+f"(d[o + 2]), "+f"(d[o + 3]), "+f"(d[o + 4]), "+f"(d[o + 5]), "+f"(d[o + 6]), "+f"(d[o + 7])
#define L8 "%0,%1,%2,%3,%4,%5,%6,%7"
#define L32 L8 ",%8,%9,%10,%11,%12,%13,%14,%15,%16,%17,%18,%19,%20,%21,%22,%23,%24,%25,%26,%27,%28,%29,%30,%31"
#define L56 L32 ",%32,%33,%34,%35,%36,%37,%38,%39,%40,%41,%42,%43,%44,%45,%46,%47,%48,%49,%50,%51,%52,%53,%54,%55"
#define L64 L56 ",%56,%57,%58,%59,%60,%61,%62,%63"

template <int O, int TA, int TB, int N> __device__ __forceinline__ void mma128_ss(float (&d)[N], uint64_t da, uint64_t db, int sc) {
    asm volatile("{.reg .pred p; setp.ne.b32 p, %66, 0;\n"
                 "wgmma.mma_async.sync.aligned.m64n128k16.f32.bf16.bf16 {" L64 "}, %64, %65, p, 1, 1, %67, %68;}"
                 : R8(d, O), R8(d, O + 8), R8(d, O + 16), R8(d, O + 24), R8(d, O + 32), R8(d, O + 40), R8(d, O + 48), R8(d, O + 56)
                 : "l"(da), "l"(db), "r"(sc), "n"(TA), "n"(TB));
}
template <int O, int TB> __device__ __forceinline__ void mma128_rs(float (&d)[128], uint32_t a0, uint32_t a1, uint32_t a2, uint32_t a3, uint64_t db, int sc) {
    asm volatile("{.reg .pred p; setp.ne.b32 p, %69, 0;\n"
                 "wgmma.mma_async.sync.aligned.m64n128k16.f32.bf16.bf16 {" L64 "}, {%64,%65,%66,%67}, %68, p, 1, 1, %70;}"
                 : R8(d, O), R8(d, O + 8), R8(d, O + 16), R8(d, O + 24), R8(d, O + 32), R8(d, O + 40), R8(d, O + 48), R8(d, O + 56)
                 : "r"(a0), "r"(a1), "r"(a2), "r"(a3), "l"(db), "r"(sc), "n"(TB));
}
template <int TB> __device__ __forceinline__ void mma64_rs(float (&d)[32], uint32_t a0, uint32_t a1, uint32_t a2, uint32_t a3, uint64_t db, int sc) {
    asm volatile("{.reg .pred p; setp.ne.b32 p, %37, 0;\n"
                 "wgmma.mma_async.sync.aligned.m64n64k16.f32.bf16.bf16 {" L32 "}, {%32,%33,%34,%35}, %36, p, 1, 1, %38;}"
                 : R8(d, 0), R8(d, 8), R8(d, 16), R8(d, 24)
                 : "r"(a0), "r"(a1), "r"(a2), "r"(a3), "l"(db), "r"(sc), "n"(TB));
}
__device__ __forceinline__ void mma112_ss(float (&d)[64], uint64_t da, uint64_t db, int sc) {
    asm volatile("{.reg .pred p; setp.ne.b32 p, %58, 0;\n"
                 "wgmma.mma_async.sync.aligned.m64n112k16.f32.bf16.bf16 {" L56 "}, %56, %57, p, 1, 1, 0, 1;}"
                 : R8(d, 8), R8(d, 16), R8(d, 24), R8(d, 32), R8(d, 40), R8(d, 48), R8(d, 56)
                 : "l"(da), "l"(db), "r"(sc));
}
__device__ __forceinline__ void mma16_rs(float (&d)[64], uint32_t a0, uint32_t a1, uint32_t a2, uint32_t a3, uint64_t db, int sc) {
    asm volatile("{.reg .pred p; setp.ne.b32 p, %13, 0;\n"
                 "wgmma.mma_async.sync.aligned.m64n16k16.f32.bf16.bf16 {" L8 "}, {%8,%9,%10,%11}, %12, p, 1, 1, 1;}"
                 : R8(d, 0)
                 : "r"(a0), "r"(a1), "r"(a2), "r"(a3), "l"(db), "r"(sc));
}

__device__ __forceinline__ cf cmul(cf a, cf b) { return {fmaf(a.x, b.x, -a.y * b.y), fmaf(a.x, b.y, a.y * b.x)}; }
__device__ __forceinline__ cf cmulc(cf a, cf b) { return {fmaf(a.x, b.x, a.y * b.y), fmaf(a.y, b.x, -a.x * b.y)}; }
__device__ __forceinline__ cf cfma(cf a, cf b, cf c) { return {fmaf(a.x, b.x, fmaf(-a.y, b.y, c.x)), fmaf(a.x, b.y, fmaf(a.y, b.x, c.y))}; }
__device__ __forceinline__ cf csq(cf a) { return {fmaf(a.x, a.x, -a.y * a.y), (a.x * a.y) * 2.f}; }
__device__ __forceinline__ cf csel(int c, cf a, cf b) {
    cf r;
    asm("{.reg .pred p; setp.ne.s32 p, %2, 0; selp.f32 %0, %3, %5, p; selp.f32 %1, %4, %6, p;}" : "=f"(r.x), "=f"(r.y) : "r"(c), "f"(a.x), "f"(a.y), "f"(b.x), "f"(b.y));
    return r;
}
__device__ __forceinline__ cf cadd(cf a, cf b) { return {a.x + b.x, a.y + b.y}; }
__device__ __forceinline__ cf csub(cf a, cf b) { return {a.x - b.x, a.y - b.y}; }
__device__ __forceinline__ cf twice_minus(cf a, cf s) { return {fmaf(2.f, a.x, -s.x), fmaf(2.f, a.y, -s.y)}; }
__device__ __forceinline__ cf twid(int m, int M) {
    int r = ((m + M / 2) & (M - 1)) - M / 2;
    float s, c;
    __sincosf((float)r * (-6.283185307179586f / (float)M), &s, &c);
    return {c, s};
}
struct c2 { cf a, b; };
#define YF 1
__device__ __forceinline__ void fin(c2& u) { if (YF) asm volatile("pmevent 1;" : "+f"(u.a.x), "+f"(u.a.y), "+f"(u.b.x), "+f"(u.b.y)); }
__device__ __forceinline__ void fin(c2& u, c2& v) {
    if (YF) asm volatile("pmevent 1;" : "+f"(u.a.x), "+f"(u.a.y), "+f"(u.b.x), "+f"(u.b.y), "+f"(v.a.x), "+f"(v.a.y), "+f"(v.b.x), "+f"(v.b.y));
}
__device__ __forceinline__ c2 mul2(c2 u, cf t) { return {cmul(u.a, t), cmul(u.b, t)}; }
__device__ __forceinline__ c2 mul2(c2 u, c2 t) { return {cmul(u.a, t.a), cmul(u.b, t.b)}; }
__device__ __forceinline__ c2 fma2(c2 u, cf t, c2 c) { return {cfma(u.a, t, c.a), cfma(u.b, t, c.b)}; }
__device__ __forceinline__ c2 fma2(c2 u, c2 t, c2 c) { return {cfma(u.a, t.a, c.a), cfma(u.b, t.b, c.b)}; }
__device__ __forceinline__ c2 twm2(c2 u, c2 s) { return {twice_minus(u.a, s.a), twice_minus(u.b, s.b)}; }
__device__ __forceinline__ void bfly(c2& u, c2& v) { const c2 t = u; u = {cadd(t.a, v.a), cadd(t.b, v.b)}; v = {csub(t.a, v.a), csub(t.b, v.b)}; fin(u, v); }
__device__ __forceinline__ void bfly_mi(c2& u, c2& v) {
    const c2 t = u, z = v;
    u = {{t.a.x + z.a.y, t.a.y - z.a.x}, {t.b.x + z.b.y, t.b.y - z.b.x}};
    v = {{t.a.x - z.a.y, t.a.y + z.a.x}, {t.b.x - z.b.y, t.b.y + z.b.x}};
    fin(u, v);
}
__device__ __forceinline__ void bfly_s(c2& u, c2& v) {
    const float s = 0.70710678118654752f;
    const c2 t = u, z = v;
    u = {{fmaf(s, z.a.x, t.a.x), fmaf(s, z.a.y, t.a.y)}, {fmaf(s, z.b.x, t.b.x), fmaf(s, z.b.y, t.b.y)}};
    v = {{fmaf(-s, z.a.x, t.a.x), fmaf(-s, z.a.y, t.a.y)}, {fmaf(-s, z.b.x, t.b.x), fmaf(-s, z.b.y, t.b.y)}};
    fin(u, v);
}
template <class T> __device__ __forceinline__ void bfly_tw(c2& u0, c2& v0, T t0, c2& u1, c2& v1, T t1) {
    v0 = fma2(v0, t0, u0); fin(v0);
    v1 = fma2(v1, t1, u1); fin(v1);
    const c2 a = twm2(u0, v0), b = twm2(u1, v1);
    u0 = v0; u1 = v1; v0 = a; v1 = b;
    fin(v0, v1);
}
template <bool TW> __device__ __forceinline__ void dft8(c2 (&v)[8], const cf (&tw)[8]) {
    if (TW) {
#pragma unroll
        for (int n = 1; n < 4; n++) { v[n] = mul2(v[n], tw[n]); fin(v[n]); }
        bfly_tw(v[0], v[4], tw[4], v[2], v[6], tw[6]);
        bfly_tw(v[1], v[5], tw[5], v[3], v[7], tw[7]);
    } else {
#pragma unroll
        for (int n = 0; n < 4; n++) bfly(v[n], v[n + 4]);
    }
    bfly(v[0], v[2]); bfly_mi(v[4], v[6]);
    bfly(v[1], v[3]); bfly_mi(v[5], v[7]);
    v[5] = {{v[5].a.x + v[5].a.y, v[5].a.y - v[5].a.x}, {v[5].b.x + v[5].b.y, v[5].b.y - v[5].b.x}};
    v[7] = {{v[7].a.y - v[7].a.x, -v[7].a.x - v[7].a.y}, {v[7].b.y - v[7].b.x, -v[7].b.x - v[7].b.y}};
    fin(v[5], v[7]);
    bfly(v[0], v[1]); bfly_s(v[4], v[5]); bfly_mi(v[2], v[3]); bfly_s(v[6], v[7]);
    const c2 t1 = v[1], t3 = v[3];
    v[1] = v[4]; v[4] = t1; v[3] = v[6]; v[6] = t3;
}

__device__ __forceinline__ void gather(uint64_t (&fv)[4], const uint8_t* a, int n) {
    asm volatile("{.reg .pred p0, p1, p2, p3;\n"
                 "setp.ge.s32 p0, %5, 0; setp.ge.s32 p1, %5, 4; setp.ge.s32 p2, %5, 8; setp.ge.s32 p3, %5, 12;\n"
                 "@p0 ld.relaxed.gpu.global.b64 %0, [%4]; @p1 ld.relaxed.gpu.global.b64 %1, [%4+-32768];\n"
                 "@p2 ld.relaxed.gpu.global.b64 %2, [%4+-65536]; @p3 ld.relaxed.gpu.global.b64 %3, [%4+-98304];}"
                 : "+l"(fv[0]), "+l"(fv[1]), "+l"(fv[2]), "+l"(fv[3]) : "l"(a), "r"(n) : "memory");
}
__device__ __forceinline__ cf as_cf(uint64_t v) { cf r; asm("mov.b64 {%0,%1}, %2;" : "=f"(r.x), "=f"(r.y) : "l"(v)); return r; }
template <int H> __device__ __forceinline__ void prescale(float (&u)[64], const float (&d)[128], cf gam) {
#pragma unroll
    for (int i = 0; i < 32; i += 2) {
        const int r = 2 * i + 2 * H;
        c2 v = mul2(c2{{d[r], -d[64 + r]}, {d[r + 1], -d[65 + r]}}, gam);
        if (YS & 2) asm volatile("pmevent 1;" : "+f"(v.a.x), "+f"(v.a.y), "+f"(v.b.x), "+f"(v.b.y));
        u[i] = v.a.x; u[32 + i] = v.a.y; u[i + 1] = v.b.x; u[33 + i] = v.b.y;
    }
}
__device__ __forceinline__ void scan2(const float (&u)[64], cf lam, cf st, const uint8_t* hptr, uint32_t hm, uint32_t hb, uint32_t& keep) {
    uint32_t hp[32];
#pragma unroll
    for (int jj = 0; jj < 4; jj++) {
        cf v[8];
#pragma unroll
        for (int i = 0; i < 8; i++) v[i] = st = cfma(lam, st, {u[8 * jj + i], u[32 + 8 * jj + i]});
        const int o = 8 * jj;
        hp[o] = pk(v[0].x, v[2].x); hp[o + 1] = pk(v[4].x, v[6].x); hp[o + 2] = pk(v[1].x, v[3].x); hp[o + 3] = pk(v[5].x, v[7].x);
        hp[o + 4] = pk(v[0].y, v[2].y); hp[o + 5] = pk(v[4].y, v[6].y); hp[o + 6] = pk(v[1].y, v[3].y); hp[o + 7] = pk(v[5].y, v[7].y);
        hp[o + jj] = (hp[o + jj] & hm) | hb;
        hp[o + 4 + jj] = (hp[o + 4 + jj] & hm) | hb;
        stg128(hptr + (jj >> 1) * 8192 + (jj & 1) * 512, hp[o], hp[o + 1], hp[o + 2], hp[o + 3]);
        stg128(hptr + 16384 + (jj >> 1) * 8192 + (jj & 1) * 512, hp[o + 4], hp[o + 5], hp[o + 6], hp[o + 7]);
        YIELD_S3();
        if (jj > 0) {
#pragma unroll
            for (int i = o - 8; i < o; i += 2) asm volatile("lop3.b32 %0, %0, %1, %2, 0x80;" : "+r"(keep) : "r"(hp[i]), "r"(hp[i + 1]));
        }
    }
}

__device__ __forceinline__ int pos_of(int n) { return (n & 24) + 4 * (n & 1) + ((n >> 1) & 3); }
__device__ __forceinline__ int unit_of(int role, int u, int& slot) {
    const int g = role & 7, w = (role >> 3) & 3, b = role >> 5;
    slot = role >= 128 ? g : (g ? 16 * g + w + 4 * b : 4 * w + b);
    return role >= 128 ? 32 * max(2 * g + u, 1) : (g ? g + 16 * w : ((w & 1) << 4) + ((w & 2) << 2)) + 64 * b + 256 * u;
}
template <int STRIDE> __device__ __forceinline__ bool tags_ok(uint32_t a, uint32_t ep) {
    uint32_t v[4], ok;
#pragma unroll
    for (int i = 0; i < 4; i++) {
        if (STRIDE || !i) asm volatile("ld.shared.u32 %0, [%1];" : "=r"(v[i]) : "r"(a + i * STRIDE) : "memory");
        else v[i] = v[0];
    }
    asm volatile("{.reg .pred p; .reg .b32 a, b; lop3.b32 a, %1, %2, %5, 0x7e; lop3.b32 b, %3, %4, %5, 0x7e; lop3.b32 a, a, b, 1, 0xa8;\n"
                 "setp.eq.u32 p, a, 0; vote.sync.all.pred p, p, -1; selp.u32 %0, 1, 0, p;}" : "=r"(ok) : "r"(v[0]), "r"(v[1]), "r"(v[2]), "r"(v[3]), "r"(ep));
    return ok;
}
__device__ __forceinline__ void load_w_rows(uint32_t dst, const CUtensorMap* mr, const CUtensorMap* mi, int kap, uint32_t bar) {
    mbar_expect_tx(bar, 16 * WPITCH);
#pragma unroll 1
    for (int i = 0; i < 2; i++, dst += 8 * WPITCH, kap = (512 - kap) & 511) {
        tma2d(dst, mr, (kap * 1026 >> 4) * 2, 0, bar);
        tma2d(dst + 4 * WPITCH, mi, (kap * 1026 >> 4) * 2, 0, bar);
    }
}
__device__ __forceinline__ void prefetch_w_rows(const CUtensorMap* mr, const CUtensorMap* mi, int kap) {
#pragma unroll 1
    for (int i = 0; i < 2; i++, kap = (512 - kap) & 511) {
        asm volatile("cp.async.bulk.prefetch.tensor.2d.L2.global [%0, {%1,%2}];" ::"l"(mr), "r"((kap * 1026 >> 4) * 2), "r"(0) : "memory");
        asm volatile("cp.async.bulk.prefetch.tensor.2d.L2.global [%0, {%1,%2}];" ::"l"(mi), "r"((kap * 1026 >> 4) * 2), "r"(0) : "memory");
    }
}
__device__ __forceinline__ void store_unit(const uint32_t (&vo)[32], const uint8_t* vp, int role, int im, uint32_t bars, unsigned* cnt) {
    warp_arrive(bars + B_STG);
    const int odd = (fresh_lane() >> 2) & 1;
    const bool pa = role || !odd, pb = role || odd == im;
#pragma unroll
    for (int k = 0; k < 16; k++) {
        if (k == (im ? VPOS : VPOS0))
            asm volatile("{.reg .pred p; setp.ne.and.u32 p, %1, 0, p0; @p red.relaxed.gpu.global.add.u32 [%0], 1;}" ::"l"(cnt), "r"(role + im) : "memory");
        asm volatile("{.reg .pred p; setp.ne.u32 p, %3, 0; @p st.global.v2.b32 [%0], {%1,%2};}" ::"l"(vp + (k >> 2) * (1 << 20) + ((k >> 1) & 1) * 8192 + (k & 1) * (4 * 32768)), "r"(vo[2 * k]), "r"(vo[2 * k + 1]), "r"((int)(k < 4 ? pa : pb)) : "memory");
    }
}
#define SB0 1024
__device__ __forceinline__ uint64_t ring_desc(uint32_t sb, uint32_t off, uint32_t lbo, uint32_t swz) {
    uint64_t d;
    asm volatile("{.reg .b32 z; shr.u32 z, %1, 28; mov.b64 %0, {z, z}; add.u64 %0, %0, %2;}" : "=l"(d) : "r"(sb), "l"(mkdesc(SB0 + off, lbo, 1024, swz)));
    return d;
}
struct Ring {
    uint32_t full, rel;
    uint32_t n;
    bool sig;
};
__device__ __forceinline__ void ring_release(const Ring& r, uint32_t o) {
    if (r.sig) asm volatile("mbarrier.arrive.shared::cluster.b64 _, [%0];" ::"r"(r.rel + o) : "memory");
}
__device__ __forceinline__ void peek(uint32_t a, uint32_t ph) { asm volatile("mbarrier.test_wait.parity.shared::cta.b64 pk, [%0], %1;" ::"r"(a), "r"(ph) : "memory"); }
__device__ __forceinline__ void peek_wait(uint32_t a, uint32_t ph, uint32_t& n) {
    asm volatile("{@pk bra DONE;\n"
                 "LOOP: mbarrier.try_wait.parity.shared::cta.b64 pk, [%1], %2; add.u32 %0, %0, 1; setp.gt.or.u32 pk, %0, %3, pk; @!pk bra LOOP;\n"
                 "DONE: }" : "+r"(n) : "r"(a), "r"(ph), "n"(SPIN_LIMIT) : "memory");
}
#define SL(k) ((k) % NST)
#define PH(k) (((k) / NST) & 1)
#define HANDPOS 5
#define H64 "%64,%65,%66,%67,%68,%69,%70,%71,%72,%73,%74,%75,%76,%77,%78,%79,%80,%81,%82,%83,%84,%85,%86,%87,%88,%89,%90,%91,%92,%93,%94,%95," \
            "%96,%97,%98,%99,%100,%101,%102,%103,%104,%105,%106,%107,%108,%109,%110,%111,%112,%113,%114,%115,%116,%117,%118,%119,%120,%121,%122,%123,%124,%125,%126,%127"
#define WG_MMA "wgmma.mma_async.sync.aligned.m64n128k16.f32.bf16.bf16 "
#define DESC_B(S, j) "mov.b64 {t, hb}, %130; mov.b64 db, {%137 + 2048 * " #S " + 2 * " #j ", hb};\n"
#define MMA_LO(S, j, p) "add.u64 da, %129, 2048 * " #S " + %136 * " #j ";" DESC_B(S, j) WG_MMA "{" L64 "}, da, db, " #p ", 1, 1, %138, 0;\n"
#define MMA_HI(S, j, p) "add.u64 da, %129, 2048 * " #S " + 512 + %136 * " #j ";\n" WG_MMA "{" H64 "}, da, db, " #p ", 1, 1, %138, 0;\n"
#define STEP(S, P, N, ph, pa, pr, X, Y) \
    "wgmma.fence.sync.aligned;\n" MMA_LO(S, 0, pa) MMA_HI(S, 0, pa) \
    "wgmma.commit_group.sync.aligned; wgmma.wait_group.sync.aligned 1; @" #pr " mbarrier.arrive.shared::cluster.b64 _, [%132 + 8 * " #P "];\n" MMA_LO(S, 1, 1) \
    "mbarrier.test_wait.parity.shared::cta.b64 pk, [%131 + 8 * " #N "], " #ph ";\n" MMA_HI(S, 1, 1) MMA_LO(S, 2, 1) X MMA_HI(S, 2, 1) MMA_LO(S, 3, 1) MMA_HI(S, 3, 1) \
    "wgmma.commit_group.sync.aligned;\n" P4A Y "@pk bra GO" #S ";\n" \
    "WAIT" #S ": mbarrier.try_wait.parity.shared::cta.b64 pk, [%131 + 8 * " #N "], " #ph "; add.u32 %128, %128, 1; setp.gt.or.u32 pk, %128, %139, pk; @!pk bra WAIT" #S ";\n" \
    "GO" #S ":\n" P4B
#define P4A
#define P4B
#define P4I
#define P4O
#define STEP_ARGS(TA) \
    : R8(d, 0), R8(d, 8), R8(d, 16), R8(d, 24), R8(d, 32), R8(d, 40), R8(d, 48), R8(d, 56), \
      R8(d, 64), R8(d, 72), R8(d, 80), R8(d, 88), R8(d, 96), R8(d, 104), R8(d, 112), R8(d, 120), "+r"(r.n) \
    : "l"(ha), "l"(hb), "r"(r.full), "r"(r.rel), "r"((uint32_t)r.sig), "r"(wg), \
      "n"(SB0 / 16 + (TA ? 32 << 16 : 1 << 16)), "n"(TA ? 128 : 2), "n"(SB0 / 16 + 1024 + (1 << 16)), "n"(TA), "n"(SPIN_LIMIT) P4O \
    : "memory"
#define STEP_REGS "{.reg .b32 k, t, ph, hb; .reg .b64 da, db; .reg .pred ps, pl, pa, pr;\n" P4I "setp.ne.u32 ps, %133, 0;\n"
__device__ __forceinline__ void gemm1(float (&d)[128], Ring& r, uint64_t ha, uint64_t hb, int wg) {
    asm volatile(STEP_REGS "mul.lo.u32 k, %134, 15; mov.b32 ph, %134; setp.ne.u32 pl, k, 0; @pl bra ONE;\n"
                 "LOOP: setp.ne.u32 pa, k, 0; and.pred pr, pa, ps; setp.eq.u32 pl, k, 15;\n"
                 STEP(0, 4, 1, ph, pa, pr, "@pl bar.arrive 1, 256;\n", "@pl bra END;\n")
                 "ONE: setp.ne.u32 pa, k, 15; and.pred pr, pa, ps; setp.eq.u32 pl, k, 30;\n"
                 STEP(1, 0, 2, ph, pa, pr, "@pl bar.arrive 2, 256;\n", "@pl bra END;\n")
                 STEP(2, 1, 3, ph, 1, ps, "", "") STEP(3, 2, 4, ph, 1, ps, "", "") "xor.b32 ph, ph, 1; add.u32 k, k, 5;\n" STEP(4, 3, 0, ph, 1, ps, "", "")
                 "bra LOOP;\n"
                 "END:\n" P4B "}" STEP_ARGS(0));
}
__device__ __forceinline__ void gemm2(float (&d)[128], Ring& r, uint64_t ha, uint64_t hb, int wg) {
    asm volatile(STEP_REGS "mov.b32 k, 0; mov.b32 ph, 0;\n"
                 "LOOP: setp.ne.u32 pa, k, 0; and.pred pr, pa, ps; setp.eq.u32 pl, k, 5;\n"
                 STEP(2, 1, 3, ph, pa, pr, "", "") STEP(3, 2, 4, ph, 1, ps, "", "") "xor.b32 ph, ph, 1; add.u32 k, k, 1;\n" STEP(4, 3, 0, ph, 1, ps, "", "")
                 "@pl bra END;\n" STEP(0, 4, 1, ph, 1, ps, "", "") STEP(1, 0, 2, ph, 1, ps, "", "")
                 "bra LOOP;\n"
                 "END: }" STEP_ARGS(1));
}
template <int O, int K, int J> __device__ __forceinline__ void mma_h(float (&y)[128], uint64_t a, uint64_t b) { mma128_ss<O, 1, 0>(y, a + SL(K) * 2048 + O * 8 + 128 * J, b + SL(K) * 2048 + 2 * J, 1); }
template <int O, int K> __device__ __forceinline__ void half_step(float (&y)[128], uint64_t a, uint64_t b) { mma_h<O, K, 0>(y, a, b); mma_h<O, K, 1>(y, a, b); mma_h<O, K, 2>(y, a, b); mma_h<O, K, 3>(y, a, b); }
template <int R, int U> __device__ __forceinline__ void out_piece(float (&y)[128], const uint32_t (&dd)[16], uint32_t x0, uint32_t x1, float* op) {
    const int i = 64 * (R >> 1) + 8 * U + 2 * (R & 1);
    asm("mul.rn.bf16x2 %0, %0, %1;" : "+r"(x0) : "r"(dd[2 * U]));
    asm("mul.rn.bf16x2 %0, %0, %1;" : "+r"(x1) : "r"(dd[2 * U + 1]));
    asm volatile("st.global.v4.f32 [%0], {%1,%2,%3,%4};" ::"l"(op + (32 * (R & 1) + 16 * (R >> 1)) * 2048 + 16 * U),
                 "f"(y[i] + __uint_as_float(x0 << 16)), "f"(y[i + 1] + __uint_as_float(x0 & 0xffff0000u)),
                 "f"(y[i + 4] + __uint_as_float(x1 << 16)), "f"(y[i + 5] + __uint_as_float(x1 & 0xffff0000u)) : "memory");
}
template <int R, int U0> __device__ __forceinline__ void load_x4(uint32_t (&xx)[8], uint32_t xa) {
#pragma unroll
    for (int u = 0; u < 4; u++)
        asm volatile("ld.shared.v2.b32 {%0,%1}, [%2];" : "=r"(xx[2 * u]), "=r"(xx[2 * u + 1]) : "r"((xa ^ (u << 5)) + (3 - R) * 8192 + U0 * 1024) : "memory");
}
__device__ __forceinline__ Ring ring_at(uint32_t sb, int k) {
    Ring r;
    r.n = 0;
    r.full = sb + OFF_BAR + B_FULL;
    asm("mapa.shared::cluster.u32 %0, %1, %2;" : "=r"(r.rel) : "r"(sb + OFF_BAR + B_EMPTY), "r"((threadIdx.x >> 5) & 1));
    r.sig = __shfl_sync(~0u, threadIdx.x & 95, threadIdx.x) == 0;
    return r;
}

template <bool BY_SM> __global__ void __cluster_dims__(2, 1, 1) __launch_bounds__(512, 1)
fused_kernel(const __grid_constant__ CUtensorMap tmX, const __grid_constant__ CUtensorMap tmBre, const __grid_constant__ CUtensorMap tmBim,
             const __grid_constant__ CUtensorMap tmCre, const __grid_constant__ CUtensorMap tmCim, const __grid_constant__ CUtensorMap tmXd,
             const __grid_constant__ CUtensorMap tmUst,
             const __grid_constant__ CUtensorMap tmWr, const __grid_constant__ CUtensorMap tmWi, const __grid_constant__ CUtensorMap tmXa,
             const Params p) {
    extern __shared__ __align__(1024) uint8_t smraw[];
    asm volatile(".reg .pred pk, p0;");
    const int tid = TIDMAP, rank = blockIdx.x & 1;
    const uint32_t wi = __shfl_sync(~0u, smem_u32(smraw) + (tid >> 5), 0), sb = wi & ~15u, bars = sb + OFF_BAR;
    const int wg = (wi >> 2) & 3, w = wi & 3, lane = tid & 31, g = lane >> 2, q = lane & 3;
    if (wg != 3) asm volatile("barrier.cluster.arrive.relaxed.aligned; barrier.cluster.wait.aligned;" ::: "memory");
    else asm volatile("prefetch.tensormap [%0];" ::"l"(w == 0 ? &tmX : w == 1 ? &tmBre : &tmBim) : "memory");
    int role;
    {
        uint32_t T = blockIdx.x;
        if (BY_SM) asm("mov.u32 %0, %%smid;" : "=r"(T));
        T >>= 1;
        const uint32_t a = ((T - 32) * 37) >> 8;
        asm("{.reg .pred p; setp.lt.u32 p, %1, 62; selp.u32 %0, 4, -58, p; add.u32 %0, %0, %1;\n"
            "setp.lt.u32 p, %1, 60; selp.u32 %0, %2, %0, p; setp.lt.u32 p, %1, 32; selp.u32 %0, %3, %0, p;}"
            : "=&r"(role) : "r"(T), "r"(8 * (T - 31 - 7 * a) + 4 + a), "r"(8 * (T & 7) + (T >> 3)));
        role = 2 * role + rank;
    }
    const bool spare = role >= 128;
    const int tc = ((role >> 3) & 14) + rank, cb = (role >> 1) & 7;
    const int fb = role >> 5, fcb = role & 31, fpos = pos_of(fcb);
    const int nu = role == 128 ? 1 : (fcb || !role ? 2 : 0);

    if (wg == 3) {
        if (elect_one()) {
            const uint32_t b = bars + w * 8;
            STAMP5(57);
            mbar_init(b, 1);
            if (w < 2 && !spare) {
                mbar_expect_tx(b, 32768);
                tma5d(sb + w * 32768 + 16384, &tmX, w * 64, 0, 0, 0, tc, b);
                if (w == 0) { tma4d(sb, &tmBre, 0, 0, 0, cb * 4, b); tma4d(sb + 8192, &tmBim, 0, 0, 0, cb * 4, b); }
                STAMP5(58);
            }
#pragma unroll
            for (int o = 32; o < B_EPOCH; o += 32) mbar_init(b + o, o < B_EMPTY ? 1 : (o < B_STG ? 2 : (o < B_P3M ? 4 : 8)));
            asm volatile("fence.mbarrier_init.release.cluster;" ::: "memory");
        }
        __syncwarp();
        STAMP5(59);
        asm volatile("barrier.cluster.arrive.relaxed.aligned;" ::: "memory");
    }
    if (opaque32(wg) == 3) {
        asm volatile("setmaxnreg.dec.sync.aligned.u32 24;");
        asm volatile("barrier.cluster.wait.aligned;" ::: "memory");
        if (w == 0) {
            if (!spare && elect_one()) {
                STAMP(56);
#pragma unroll 1
                for (int k = 1; k < NST; k++) {
                    if (k >= 2) mbar_expect_tx(bars + B_FULL + k * 8, 32768);
                    tma4d_mc(sb + k * 32768 + rank * 8192, rank ? &tmBim : &tmBre, k * 64, 0, 0, cb * 4, bars + B_FULL + k * 8);
                    if (k >= 2) tma5d(sb + k * 32768 + 16384, &tmX, k * 64, 0, 0, 0, tc, bars + B_FULL + k * 8);
                }
#define RING_WAIT "mbarrier.try_wait.parity.shared::cta.b64 p, [fb + 256], ph; @p bra GO;\n" \
                  "WAIT: mbarrier.try_wait.parity.shared::cta.b64 p, [fb + 256], ph; add.u32 n, n, 1; setp.gt.or.u32 p, n, 32768, p; @!p bra WAIT;\nGO:\n"
#define RING_NEXT "pmevent 1; add.u32 o, o, 8; setp.eq.u32 p, o, 40; selp.u32 o, 0, o, p; @p xor.b32 ph, ph, 1; add.u32 fb, %1, o; shl.b32 t, o, 12; add.u32 da, %0, t;\n"
                asm volatile("{.reg .b32 o, k, kk, c2, da, db, fb, ph, n, t; .reg .pred p;\n"
                             "mov.b32 o, 0; mov.b32 k, 320; mov.b32 kk, 320; mov.b32 c2, 0; mov.b32 ph, 0; mov.b32 n, 0; mov.b32 fb, %1; mov.b32 da, %0; mov.b32 db, %2;\n"
                             "LOOP:\n" RING_WAIT
                             "cp.async.bulk.tensor.5d.shared::cluster.global.mbarrier::complete_tx::bytes [da], [%3, {kk,0,0,0,%5}], [fb];\n"
                             "cp.async.bulk.tensor.4d.shared::cluster.global.mbarrier::complete_tx::bytes.multicast::cluster [db], [%4, {kk,0,c2,%6}], [fb], %7;\n"
                             "mbarrier.arrive.expect_tx.shared::cta.b64 _, [fb], 32768;\n" RING_NEXT
                             "add.u32 db, %2, t; add.u32 k, k, 64; and.b32 kk, k, 1023; shr.u32 c2, k, 9; and.b32 c2, c2, 2; setp.ne.u32 p, k, 2048; @p bra LOOP;}"
                             ::"r"(sb + 16384), "r"(bars + B_FULL), "r"(sb + rank * 8192), "l"(&tmX), "l"(rank ? &tmBim : &tmBre), "r"(tc), "r"(cb * 4), "h"((uint16_t)3) : "memory");
                asm volatile("{.reg .b32 o, k, kk, da, db, fb, hb, ph, n, t; .reg .b64 m, src; .reg .pred p;\n"
                             "mov.b32 o, 16; mov.b32 k, 0; mov.b32 kk, 0; mov.b32 ph, 1; mov.b32 n, 0; add.u32 fb, %1, 16; add.u32 hb, %1, 72; add.u32 da, %0, 65536; add.u32 db, %2, 65536;\n"
                             "mov.b64 m, %3; mov.b64 src, %5;\n"
                             "GROUP: add.u32 t, %8, k;\n"
                             "OWN: mbarrier.try_wait.parity.shared::cta.b64 p, [t], 0; add.u32 n, n, 1; setp.gt.or.u32 p, n, 32768, p; @!p bra OWN;\n"
                             "LOOP:\n" RING_WAIT
                             "cp.async.bulk.shared::cluster.global.mbarrier::complete_tx::bytes [da], [src], 16384, [hb];\n"
                             "cp.async.bulk.tensor.5d.shared::cluster.global.mbarrier::complete_tx::bytes.multicast::cluster [db], [m, {kk,0,0,0,%6}], [fb], %7;\n"
                             "mbarrier.expect_tx.shared::cta.b64 [fb], 16384; mbarrier.arrive.expect_tx.shared::cta.b64 _, [hb], 16384;\n" RING_NEXT
                             "add.u32 db, %2, t; add.u64 src, src, 16384; sub.u64 m, %4, m; add.u32 k, k, 1; shl.b32 kk, k, 5; and.b32 kk, kk, 0x7c0;\n"
                             "and.b32 t, k, 1; mad.lo.u32 hb, t, 8, fb; add.u32 hb, hb, o; add.u32 hb, hb, 40;\n"
                             "and.b32 t, k, 7; setp.ne.u32 p, t, 0; @p bra LOOP; setp.ne.u32 p, k, 32; @p bra GROUP;}"
                             ::"r"(sb), "r"(bars + B_FULL), "r"(sb + 16384 + rank * 8192), "l"(&tmCre), "l"((uint64_t)&tmCre + (uint64_t)&tmCim),
                               "l"(g_H + (size_t)tc * 32 * 16384), "r"(cb * 8 + rank * 4), "h"((uint16_t)3), "r"(bars + B_HOWN) : "memory");
            }
        } else if (opaque32(w) == 1) {
            const unsigned ep = ld_rlx(g_epoch + role * 8) + 1;
            __syncwarp();
            if (elect_one()) {
                asm volatile("st.relaxed.gpu.global.u32 [%0], %1;" ::"l"(g_epoch + role * 8), "r"(ep) : "memory");
                asm volatile("st.shared.u32 [%0], %1;" ::"r"(bars + B_EPOCH), "r"(ep) : "memory");
                mbar_arrive(bars + B_EP);
            }
            int slot;
            const int kap = unit_of(role, 0, slot), kap1 = unit_of(role, 1, slot);
            uint32_t lph = 0;
            if (!spare) mbar_wait(bars + B_STGU, 0);
            STAMP(21);
#pragma unroll 1
            for (int e = 0; e < 4; e++) {
                if (e < 2 && elect_one()) {
                    if (!spare) {
                        const uint32_t src = sb + OFF_P + e * 16384;
                        const int c0 = fb * 2048 + fpos * 64;
                        if (e == 0) {
#pragma unroll 1
                            for (int r = 4; r < 8; r++) bulk_st(g_X + r * (32 * 16384) + c0 * 2, src + r * 4096, 128);
                        }
                        tma2d_st(&tmUst, c0, e * 128, src);
                        bulk_commit();
                        tma2d_st(&tmUst, c0, e * 128 + 64, src + 8192);
                        bulk_commit();
                        if (UHINT) asm volatile("cp.async.bulk.wait_group.read 1;" ::: "memory");
                        red_hint(g_cnt + e * 32);
                    }
                    if (e == 0) {
                        mbar_expect_tx(bars + B_FG, 8192);
                        bulk_ld(sb + OFF_F, (const uint8_t*)g_tab + TAB_FG, 8192, bars + B_FG);
                    }
                }
                if (!e) STAMP(40);
                if (e >= 2) {
                    if (e - 2 < nu) mbar_wait(bars + B_WFREE, e & 1);
                    if (e == 2) {
                        if (nu == 2 && elect_one()) load_w_rows(sb + OFF_WD, &tmWr, &tmWi, kap1, bars + B_WD);
                    } else if (!spare) {
                        mbar_wait(bars + B_HOWN + 8, 0);
#pragma unroll 1
                        for (int r = 0; r < 3; r++) {
                            if (elect_one()) {
                                if (r == 0) { mbar_expect_tx(bars + B_XD, 24576 + 256); bulk_ld(sb + OFF_LAM, p.dsk + cb * 128, 256, bars + B_XD); }
                                tma4d(sb + OFF_F + (3 - r) * 8192, &tmXd, 0, tc * 128 + 32 * (r & 1) + 16 * (r >> 1), 0, cb * 2, bars + B_XD);
                            }
                            __nanosleep(PACE_X);
                        }
                    }
                    if (e - 2 < nu) mbar_wait(bars + B_STG, e & 1);
                    STAMPO(23, e - 2);
                    if (e == 3 && !spare && elect_one()) {
                        mbar_expect_tx(bars + B_FG, 8192);
                        bulk_ld(sb + OFF_F, (const uint8_t*)g_tab + TAB_G + fb * 8192, 8192, bars + B_FG);
                    }
                }
                const uint32_t tg = e < 2 ? lane * 128 + ((((lane >> 1) & 2) ^ (lane & 3)) << 4) + (lane >> 3) * 4 : lane * 64 + (lane & 8) * 4 + (lane & 2) * 8 + (lane & 4) * 2;
                if (spare) {
                    if (e == 1) {
                        wait_cnt(g_cnt, 128 * ep);
                        STAMP(42);
#pragma unroll 1
                        for (int n = 0; n < 4096; n++) {
                            if (elect_one()) {
                                mbar_expect_tx(bars + B_LD, 8 * 16384);
#pragma unroll 1
                                for (int r = 0; r < 8; r++) bulk_ld(sb + r * 16384, g_X + (size_t)r * (32 * 16384), 16384, bars + B_LD);
                            }
                            mbar_wait(bars + B_LD, n & 1);
                            bool ok = true;
#pragma unroll 1
                            for (int r = 0; r < 8; r++) ok &= tags_ok<4096>(sb + r * 16384 + tg, ep);
                            if (ok) break;
                        }
                        if (elect_one()) mbar_arrive(bars + B_RAW);
                    }
                } else if (e >= 2 || nu) {
                    const uint32_t dst = sb + OFF_P + (e & 1) * 16384;
                    wait_cnt(g_cnt + e * 32, 128 * ep);
                    STAMPO(41, e == 2 ? -12 : e);
#pragma unroll 1
                    for (int n = 0; n < 4096; n++) {
                        if (elect_one()) { bulk_wait_read(); mbar_expect_tx(bars + B_LD, 16384); bulk_ld(dst, g_X + (size_t)(e < 2 ? role + e * 128 : 254 + (fb * 32 + fpos) * 2 + e) * 16384, 16384, bars + B_LD); }
                        mbar_wait(bars + B_LD, lph);
                        if (!e) STAMP3(49);
                        lph ^= 1;
                        if (tags_ok<4096>(dst + tg, ep) & tags_ok<4096>(dst + tg + (e & 2) * 1024, ep) & tags_ok<0>(dst + (e == 3 ? (lane & 1) * 8192 + 32 : 0), ep)) break;
                    }
                    if (role == 0 && e < 2) {
#pragma unroll 1
                        for (int i = 0; i < 16; i++) sts128(dst + i * 1024 + g * 128 + 64 + q * 16, 0, 0, 0, 0);
                        fence_async_sm();
                    }
                    if (elect_one()) mbar_arrive(bars + B_IN + e * 8);
                }
                if (e < 2 && nu && elect_one()) {
                    if (e) prefetch_w_rows(&tmWr, &tmWi, kap1);
                    else load_w_rows(sb + OFF_WD, &tmWr, &tmWi, kap, bars + B_WD);
                }
            }
            if (!spare) {
                mbar_wait(bars + B_P3M, 0);
                if (elect_one()) { mbar_expect_tx(bars + B_XD + 8, 8192); tma4d(sb + OFF_F, &tmXd, 0, tc * 128 + 48, 0, cb * 2, bars + B_XD + 8); }
            }
        } else {
            if (w == 2) {
                {
                    const int u = lane >> 4;
                    int slot;
                    const int r0 = unit_of(role, u, slot) + 512 * ((lane >> 1) & 3), r1 = (2048 - r0) & 2047, mir = (lane >> 3) & 1;
                    const unsigned short* wp = (const unsigned short*)((lane & 1) ? p.wi : p.wr);
                    const float a = bf2f(wp[r0 * 513 + mir * 512]), b = bf2f(wp[r1 * 513 + mir * 512]);
                    asm volatile("st.shared.f32 [%0], %1;" ::"r"(sb + OFF_WSP + u * 64 + (lane & 15) * 4), "f"(0.5f * ((lane & 1) ? (mir ? b - a : a - b) : a + b)) : "memory");
                }
                warp_arrive(bars + B_WSP);
            } else if (!spare) {
                if (XA_T0) __nanosleep(XA_T0);
#pragma unroll 1
                for (int i = 0; i < 8; i++) {
                    if (i >= XA_N0) __nanosleep(XA_PACE);
                    if (elect_one()) {
                        if (i == 0) mbar_expect_tx(bars + B_XIN, 32768);
                        tma3d(sb + OFF_F + i * 4096, &tmXa, fcb * 32, 0, 4 * i + fb, bars + B_XIN);
                    }
                }
            }
            if (!spare) {
                if (w == 2 && nu) {
                    mbar_wait(bars + B_STGU, 0);
                    int slot;
                    const int kap = unit_of(role, 0, slot);
                    if (elect_one()) prefetch_w_rows(&tmWr, &tmWi, kap);
                }
                const unsigned ep = get_epoch(bars);
#define CNT_RETRY
#define CNT_ARG
                asm volatile("{.reg .b32 o, k, hb, fb, ca, m, ph, rph, n, t, v0, v1, v2, v3; .reg .b64 src; .reg .pred p, pe;\n"
                             "elect.sync _|pe, 0xffffffff; mov.b32 o, %0; shr.u32 k, %0, 3; sub.u32 k, k, 2; mov.b32 m, 0x107c0; mov.b32 rph, 0; mov.b32 n, 0;\n"
                             "bra NEXT;\n"
                             "LOOP: mbarrier.try_wait.parity.shared::cta.b64 p, [hb], ph; @p bra GO;\n"
                             "WAIT: mbarrier.try_wait.parity.shared::cta.b64 p, [hb], ph; add.u32 n, n, 1; setp.gt.or.u32 p, n, 32768, p; @!p bra WAIT;\n"
                             "GO: ld.shared.u32 v0, [ca]; ld.shared.u32 v1, [ca + 128]; ld.shared.u32 v2, [ca + 256]; ld.shared.u32 v3, [ca + 384];\n"
                             "lop3.b32 v0, v0, v1, %4, 0x7e; lop3.b32 v2, v2, v3, %4, 0x7e; lop3.b32 v0, v0, v2, 1, 0xa8; setp.eq.u32 p, v0, 0; vote.sync.all.pred p, p, -1; @p bra OK;\n"
                             CNT_RETRY "add.u32 n, n, 16; setp.gt.u32 p, n, 32768; @p bra OK;\n"
                             "shl.b32 t, o, 12; add.u32 t, t, %5; mad.wide.u32 src, k, 16384, %6;\n"
                             "@pe mbarrier.arrive.expect_tx.shared::cta.b64 _, [%7], 16384; @pe cp.async.bulk.shared::cluster.global.mbarrier::complete_tx::bytes [t], [src], 16384, [%7];\n"
                             "AGAIN: mbarrier.try_wait.parity.shared::cta.b64 p, [%7], rph; add.u32 n, n, 1; setp.gt.or.u32 p, n, 32768, p; @!p bra AGAIN;\n"
                             "xor.b32 rph, rph, 1; bra GO;\n"
                             "OK: @pe mbarrier.arrive.shared::cta.b64 _, [fb]; pmevent 1;\n"
                             "add.u32 o, o, 16; setp.ge.u32 p, o, 40; @p sub.u32 o, o, 40; add.u32 k, k, 2;\n"
                             "NEXT: shr.u32 m, m, 1; and.b32 ph, m, 1; add.u32 fb, %1, o; mad.lo.u32 hb, o, 2, %2; mad.lo.u32 ca, o, 4096, %3; setp.lt.u32 p, k, 32; @p bra LOOP;}"
                             ::"r"(8 * w), "r"(bars + B_FULL), "r"(bars + B_HL - 16 + w * 8), "r"(sb + (q >> 1) * 8192 + (q & 1) * 512 + g * 1040 + q * 4), "r"(ep),
                               "r"(sb), "l"(g_H + (size_t)tc * 32 * 16384), "r"(bars + B_HR - 16 + w * 8) CNT_ARG : "memory");
                if (w == 3) warp_arrive(bars + B_DONE);
            }
        }
    } else {
        STAMP(55);
        asm volatile("setmaxnreg.inc.sync.aligned.u32 152;");
        STAMP5(60);
        const int t7 = tid & 127, hf = wg - 1;
        const int mi = lane >> 3, gl = lane & 7;
        if (spare && wg != 2) {
            if (tid < 64) { const uint4 v = __ldg((const uint4*)((const uint8_t*)g_tab + TAB_PC) + tid); sts128(sb + OFF_LAM + tid * 16, v.x, v.y, v.z, v.w); }
            bar_sync(1, 256);
            mbar_wait(bars + B_RAW, 0);
            STAMP(0);
#pragma unroll 1
            for (int u = 0; u < nu; u++) {
                int slot;
                const int t = unit_of(role, u, slot) >> 5;
                const uint32_t off = (tid >> 2) * 128 + q * 16;
                float zr[16], zi[16];
#pragma unroll
                for (int k = 0; k < 16; k++) zr[k] = zi[k] = 0.f;
#pragma unroll 1
                for (int r = (t & 1) ? 0 : t >> 1; r < 8 - ((t & 1) ? 0 : (t >> 1) - 1); r += (t & 1) ? 1 : 8 - t) {
                    float4 c;
                    float a[8], b[8];
                    lds128f(sb + OFF_LAM + t * 128 + r * 16, c.x, c.y, c.z, c.w);
                    lds128f(sb + r * 16384 + off, a[0], a[1], a[2], a[3]);
                    lds128f(sb + r * 16384 + off + 64, b[0], b[1], b[2], b[3]);
                    lds128f(sb + r * 16384 + off + 8192, a[4], a[5], a[6], a[7]);
                    lds128f(sb + r * 16384 + off + 8192 + 64, b[4], b[5], b[6], b[7]);
#pragma unroll
                    for (int k = 0; k < 16; k++) {
                        const uint32_t ua = __float_as_uint(a[k >> 1]), ub = __float_as_uint(b[k >> 1]);
                        const float x = __uint_as_float((k & 1) ? ua & 0xffff0000u : ua << 16), y = __uint_as_float((k & 1) ? ub & 0xffff0000u : ub << 16);
                        zr[k] = fmaf(c.x, x, fmaf(c.z, y, zr[k]));
                        zi[k] = fmaf(c.y, x, fmaf(c.w, y, zi[k]));
                    }
                }
                const uint32_t dst = sb + OFF_P + u * 16384 + off;
#pragma unroll
                for (int k = 0; k < 16; k += 8) {
                    sts128(dst + k * 1024, pk(zr[k], zr[k + 1]), pk(zr[k + 2], zr[k + 3]), pk(zr[k + 4], zr[k + 5]), pk(zr[k + 6], zr[k + 7]));
                    sts128(dst + k * 1024 + 64, pk(zi[k], zi[k + 1]), pk(zi[k + 2], zi[k + 3]), pk(zi[k + 4], zi[k + 5]), pk(zi[k + 6], zi[k + 7]));
                }
                fence_async_sm();
                bar_sync(1, 256);
                if (tid == 0) mbar_arrive(bars + B_IN + u * 8);
                STAMPO(1, u);
            }
            return;
        }
        if (wg == 2 && !spare) {
            asm volatile("setmaxnreg.inc.sync.aligned.u32 176;");
            uint32_t f1[16];
            cf tw[8];
            if (TAB_T0) __nanosleep(TAB_T0);
            ldtab<4, 2048>(f1, TAB_F1 + t7 * 16);
            ldtab_cf<16>(tw, TAB_TW1 + (t7 >> 2) * 64);
            const uint32_t ep = get_epoch(bars);
            uint32_t a0 = sb + OFF_P + (8 * w + gl + 32 * (mi >> 1)) * 128 + (((((mi & 1) << 2) | (fpos & 3)) ^ gl) << 4);
            float acc[128];
            const uint64_t dx = opaque(mkdesc(sb + OFF_F, 4096, 512, 2));
            mbar_wait(bars + B_XIN, 0);
            STAMP(20);
            pinu(f1);
            wg_fence();
#pragma unroll
            for (int j = 0; j < 4; j++) {
                mma128_rs<0, 1>(acc, f1[4 * j], f1[4 * j + 1], f1[4 * j + 2], f1[4 * j + 3], dx + j * 64, j);
                mma128_rs<64, 1>(acc, f1[4 * j], f1[4 * j + 1], f1[4 * j + 2], f1[4 * j + 3], dx + 1024 + j * 64, j);
            }
            wg_commit();
            wg_wait<0>();
            pin(acc);
            pinu(f1);
#pragma unroll 1
            for (int h = 0;; h++) {
                const uint32_t tmask = 2 * q + h == fpos >> 2 ? ~1u : ~0u, tbit = ep & ~tmask;
#pragma unroll
                for (int cl = 0; cl < 2; cl++) {
                    c2 v[8];
#pragma unroll
                    for (int n = 0; n < 8; n++) {
                        const int i = 4 * (4 * n + cl);
                        v[n] = {{acc[i], acc[i + 2]}, {acc[i + 1], acc[i + 3]}};
                    }
                    dft8<true>(v, tw);
#pragma unroll
                    for (int r = 0; r < 8; r += 2) {
                        uint32_t o0 = pk(v[r].a.x, v[r].b.x), o1 = pk(v[r].a.y, v[r].b.y), o2 = pk(v[r + 1].a.x, v[r + 1].b.x), o3 = pk(v[r + 1].a.y, v[r + 1].b.y);
                        if (cl == 0) { o0 = (o0 & tmask) | tbit; o2 = (o2 & tmask) | tbit; }
                        stsm4((a0 ^ (cl << 4)) + r * 4096, o0, o1, o2, o3);
                    }
                }
                if (h) break;
                a0 ^= 32;
#pragma unroll
                for (int n = 0; n < 8; n++) {
                    asm volatile("mov.b32 %0, %8; mov.b32 %1, %9; mov.b32 %2, %10; mov.b32 %3, %11; mov.b32 %4, %12; mov.b32 %5, %13; mov.b32 %6, %14; mov.b32 %7, %15; pmevent 1;"
                                 : "=&f"(acc[16 * n]), "=&f"(acc[16 * n + 1]), "=&f"(acc[16 * n + 2]), "=&f"(acc[16 * n + 3]), "=&f"(acc[16 * n + 4]), "=&f"(acc[16 * n + 5]), "=&f"(acc[16 * n + 6]), "=&f"(acc[16 * n + 7])
                                 : "f"(acc[16 * n + 8]), "f"(acc[16 * n + 9]), "f"(acc[16 * n + 10]), "f"(acc[16 * n + 11]), "f"(acc[16 * n + 12]), "f"(acc[16 * n + 13]), "f"(acc[16 * n + 14]), "f"(acc[16 * n + 15]));
                }
            }
            fence_async_sm();
            warp_arrive(bars + B_STGU);
            bar_sync(3, 128);
            asm volatile("setmaxnreg.dec.sync.aligned.u32 152;");
            bar_arrive(7, 256);
        }
        if (wg == 1) {
            if (LAM_T0) __nanosleep(LAM_T0);
            const int cl = tid & 127, ch = (cl >> 6) * 512 + ((cl >> 3) & 1) * 256 + cb * 32 + ((cl >> 4) & 3) * 8 + (cl & 7);
            const float lr = bf2f(*(const unsigned short*)padd(p.lre, 2 * ch)), li = bf2f(*(const unsigned short*)padd(p.lim, 2 * ch));
            const float dt = __bfloat162float(__float2bfloat16(expf(bf2f(*(const unsigned short*)padd(p.ldt, 2 * ch)))));
            const float an = dt * li, th = an * 0.318309873342514f;
            float sn, cs, inv;
            sincospif(fmaf(rintf(0.5f * th), -2.f, th) + fmaf(an, 1.2841276653e-8f, fmaf(an, 0.318309873342514f, -th)), &sn, &cs);
            const float ex = expf(dt * lr), br = ex * cs, bi = ex * sn;
            asm("rcp.approx.f32 %0, %1;" : "=f"(inv) : "f"(lr * lr + li * li));
            inv += inv;
            const float cr = ((br - 1.f) * lr + bi * li) * inv, ci = (bi * lr - (br - 1.f) * li) * inv;
            sts128(sb + OFF_LAM + cl * 16, __float_as_uint(br), __float_as_uint(-bi), __float_as_uint(cr), __float_as_uint(-ci));
            mbar_wait(bars + B_EP, 0);
            bar_sync(8, 128);
            if (tid == 128) mbar_arrive(bars + B_LAM);
        }
        if (wg != 2) {
        if (wg == 0) bar_sync(4, 128); else bar_sync(7, 256);
        asm volatile("setmaxnreg.inc.sync.aligned.u32 160;");
        if (wg == 0) bar_sync(4, 128);
        float d[128];
        if (wg == 1) bar_sync(1, 256);
        STAMPW(0, 10);
        Ring rg = ring_at(sb, role * 66 + wg * 16);
        cf lam[2];
        unsigned ep;
        mbar_wait_fast(rg.full + 8 * wg, wg);
        gemm1(d, rg, ring_desc(sb, 0, 16, 1), ring_desc(sb, 16384, 16, 1), wg);
        const uint32_t lama = sb + OFF_LAM + wg * 1024 + w * 256 + (fresh_lane() & 28) * 4;
        mbar_wait_fast(bars + B_LAM, 0);
        lam[0] = lds_cf(lama); lam[1] = lds_cf(lama + 128);
        asm volatile("ld.shared.u32 %0, [%1];" : "=r"(ep) : "r"(bars + B_EPOCH) : "memory");
        asm volatile("setmaxnreg.inc.sync.aligned.u32 176;");
        cf L[2] = {lam[0], lam[1]};
#pragma unroll
        for (int i = 0; i < 4; i++) { L[0] = csq(L[0]); L[1] = csq(L[1]); }
        asm volatile("" : "+f"(L[0].x), "+f"(L[0].y), "+f"(L[1].x), "+f"(L[1].y)::"memory");
        wg_wait<0>();
        ring_release(rg, 8 * wg);
        pin(d);
        STAMPW(1, 11);
        {
            const int lane = fresh_lane(), g = lane >> 2, q = lane & 3, mi = lane >> 3, gl = lane & 7;
            cf f[2], fb2[2];
#pragma unroll
            for (int i = 0; i < 17; i++) {
#pragma unroll
                for (int h = 0; h < 2; h++) {
                    const int r = 4 * (i >> 1) + 2 * h + (i & 1), r2 = 32 + 4 * ((i - 1) >> 1) + 2 * h + ((i - 1) & 1);
                    if (i < 16) f[h] = i ? cfma(lam[h], f[h], {d[r], -d[64 + r]}) : cf{d[r], -d[64 + r]};
                    if (i > 0) fb2[h] = i > 1 ? cfma(lam[h], fb2[h], {d[r2], -d[64 + r2]}) : cf{d[r2], -d[64 + r2]};
                    if (i && (h || !(YS & 8))) YIELD_S1();
                }
            }
            const uint8_t* cbase = (const uint8_t*)g_carry + (tc * 16 + wg * 8 + cb) * 512 + w * 64;
            const uint8_t* cptr = padd(cbase, g * 8);
            const unsigned tag = ep & 15u;
#pragma unroll
            for (int h = 0; h < 2; h++) { f[h] = cfma(L[h], f[h], fb2[h]); L[h] = csq(L[h]); }
            cf s0[2], s1[2], s2[2];
#pragma unroll
            for (int h = 0; h < 2; h++) {
                s0[h] = {__shfl_sync(~0u, f[h].x, 0, 4), __shfl_sync(~0u, f[h].y, 0, 4)};
                s1[h] = {__shfl_sync(~0u, f[h].x, 1, 4), __shfl_sync(~0u, f[h].y, 1, 4)};
                s2[h] = {__shfl_sync(~0u, f[h].x, 2, 4), __shfl_sync(~0u, f[h].y, 2, 4)};
            }
#pragma unroll
            for (int h = 0; h < 2; h++) {
                s1[h] = cfma(L[h], s0[h], s1[h]);
                s2[h] = cfma(L[h], s1[h], s2[h]);
                f[h] = cfma(L[h], s2[h], f[h]);
                asm volatile("{.reg .pred p; .reg .b64 a; setp.eq.u32 p, %3, 3; mov.b64 a, {%1,%2}; @p st.relaxed.gpu.global.b64 [%0], a;}" ::"l"(cptr + h * 256),
                             "r"((__float_as_uint(f[h].x) & ~15u) | tag), "f"(f[h].y), "r"(q) : "memory");
            }
            STAMPX(2, 12);
            cf gam = lds_cf(lama + 8);
            cf st = csel(q & 2, csel(q & 1, s2[0], s1[0]), csel(q & 1, s0[0], {0.f, 0.f}));
            const cf st1 = csel(q & 2, csel(q & 1, s2[1], s1[1]), csel(q & 1, s0[1], {0.f, 0.f}));
            cptr = padd(cbase - 4 * 8192, (3 - mi) * 8192 + gl * 8);
            const int nprev = tc - 1 - mi;
            const uint8_t* hptr = padd(g_H + (size_t)(tc * 32 + wg * 16 + (cb & 6)) * 16384 + ((cb & 1) * 4 + w) * 1024, g * 64 + ((q ^ (g >> 1)) << 4));
            const uint32_t hm = 4 * (g & 1) + (q ^ (g >> 1)) == (cb & 1) * 4 + w ? ~1u : ~0u;
            float u[64];
            uint64_t fv[4] = {tag, tag, tag, tag};
            prescale<0>(u, d, gam);
            gather(fv, cptr, nprev);
#pragma unroll 1
            for (int h = 0;; h++) {
                const cf L2 = csq(L[0]), M = csq(L2);
                cf M4 = csq(csq(M));
                M4 = {__shfl_sync(~0u, M4.x, 4 * gl), __shfl_sync(~0u, M4.y, 4 * gl)};
                cf lq = cmul(gam, cmul(csel(q & 1, L[0], {1.f, 0.f}), csel(q & 2, L2, {1.f, 0.f})));
                st = cmul(gam, st);
                asm volatile("pmevent 1;" : "+f"(lq.x), "+f"(lq.y), "+f"(st.x), "+f"(st.y));
#pragma unroll 1
                for (unsigned n = 0; __any_sync(~0u, (((uint32_t)fv[0] ^ tag) | ((uint32_t)fv[1] ^ tag) | ((uint32_t)fv[2] ^ tag) | ((uint32_t)fv[3] ^ tag)) & 15u) && n < SPIN_LIMIT; n++) gather(fv, cptr, nprev);
                if (!h) STAMPX(53, 54);
                cf P = as_cf(fv[3]), pj[4];
#pragma unroll
                for (int a = 2; a >= 0; a--) P = cfma(M4, P, as_cf(fv[a]));
                cptr += 256;
                asm volatile("" : "+f"(P.x), "+f"(P.y)::"memory");
                gather(fv, cptr, h ? -1 : nprev);
#pragma unroll
                for (int j = 3; j >= 0; j--) pj[j] = {__shfl_sync(~0u, P.x, g + 8 * j), __shfl_sync(~0u, P.y, g + 8 * j)};
                st = cfma(lq, cfma(M, cfma(M, cfma(M, pj[3], pj[2]), pj[1]), pj[0]), st);
                if (!h) STAMPX(3, 13);
                uint32_t keep = sb >> 28;
                scan2(u, lam[0], st, hptr, hm, ep & ~hm, keep);
                warp_arrive(bars + B_HOWN + wg * 16 + h * 8 + keep);
                if (h) break;
                STAMPW(4, 14);
                lds128f(lama + 128, lam[0].x, lam[0].y, gam.x, gam.y);
                st = st1;
                L[0] = L[1];
                hptr += 8 * 16384;
                prescale<1>(u, d, gam);
            }
            STAMPW(5, 15);
        }
        if (wg == 0) bar_sync(4, 128); else bar_sync(8, 128);
        if (wg == 0) {
            asm volatile("setmaxnreg.dec.sync.aligned.u32 160;");
            float y[128];
            rg = ring_at(sb, role * 66 + 32);
            STAMP(6);
            bar_sync(2, 256);
            STAMP(7);
            mbar_wait_fast(rg.full + SL(32) * 8, PH(32));
            const uint64_t dA = ring_desc(sb, 0, 512, 2), dB = ring_desc(sb, 16384, 16, 1);
            gemm2(y, rg, dA, dB, 0);
            asm volatile("setmaxnreg.inc.sync.aligned.u32 184;");
            const int lane = fresh_lane(), g = lane >> 2, q = lane & 3;
            const int pg = 2 * (g & 3) + (g >> 2);
            float* op = (float*)padd(p.out + (size_t)(tc * 128 + 64 * (w & 1) + 8 * (w >> 1)) * 2048 + 1024 + cb * 128, pg * 8192 + q * 16);
            const uint32_t xa = sb + OFF_F + (16 * (w & 1) + 8 * (w >> 1) + pg) * 128 + (((q >> 1) ^ pg) << 4) + (q & 1) * 8;
#define HALF0(k) wg_fence(); peek(k < 63 ? rg.full + SL(k + 1) * 8 : bars + B_XD, PH(k + 1)); half_step<0, k>(y, dA, dB); wg_commit(); peek_wait(k < 63 ? rg.full + SL(k + 1) * 8 : bars + B_XD, PH(k + 1), rg.n);
            HALF0(60) HALF0(61) HALF0(62) HALF0(63)
            const uint64_t dB2 = ring_desc(sb >> 1, 16384, 16, 1);
            uint32_t xa0[8], xa1[8], dd[16];
#pragma unroll
            for (int i = 0; i < 8; i++) asm volatile("ld.shared.v2.b32 {%0,%1}, [%2];" : "=r"(dd[2 * i]), "=r"(dd[2 * i + 1]) : "r"(sb + OFF_LAM + q * 8 + 32 * i) : "memory");
            load_x4<0, 0>(xa0, xa);
            wg_fence();
            half_step<64, 64 - SKEW>(y, dA, dB2);
            wg_commit();
            wg_wait<1>();
#pragma unroll
            for (int i = 0; i < 64; i++) asm volatile("" : "+f"(y[i])::"memory");
            STAMP(16);
#define MM(n) if (4 + (n) < 4 * SKEW) { wg_fence(); mma_h<64, 65 - SKEW + (n) / 4, (n) % 4>(y, dA, dB2); mma_h<64, 65 - SKEW + (n) / 4, (n) % 4 + 1>(y, dA, dB2); }
#define OUT4(R, U, X, n) out_piece<R, U>(y, dd, X[0], X[1], op); MM(n) out_piece<R, U + 1>(y, dd, X[2], X[3], op); MM(n + 2) \
                         out_piece<R, U + 2>(y, dd, X[4], X[5], op); MM(n + 4) out_piece<R, U + 3>(y, dd, X[6], X[7], op); MM(n + 6)
            load_x4<0, 4>(xa1, xa);
            OUT4(0, 0, xa0, 0)
            load_x4<1, 0>(xa0, xa);
            OUT4(0, 4, xa1, 8)
            wg_commit();
            load_x4<1, 4>(xa1, xa);
            OUT4(1, 0, xa0, 16)
            load_x4<2, 0>(xa0, xa);
            OUT4(1, 4, xa1, 16)
            STAMP(18);
            wg_wait<0>();
#pragma unroll
            for (int i = 64; i < 128; i++) asm volatile("" : "+f"(y[i])::"memory");
            STAMP(8);
            load_x4<2, 4>(xa1, xa);
            mbar_wait_fast(bars + B_XD + 8, 0);
            OUT4(2, 0, xa0, 16)
            load_x4<3, 0>(xa0, xa);
            OUT4(2, 4, xa1, 16)
            load_x4<3, 4>(xa1, xa);
            OUT4(3, 0, xa0, 16)
            OUT4(3, 4, xa1, 16)
            STAMP(9);
            return;
        }
        asm volatile("setmaxnreg.dec.sync.aligned.u32 152;");
        } else {
        if (nu) {
            cf T[8];
            ldtab_cf<2048>(T, TAB_T + t7 * 16);
            const uint32_t ep = get_epoch(bars);
            const int ka = pos_of(t7 >> 2);
            asm volatile("setp.eq.u32 p0, %0, 0;" ::"r"(__shfl_sync(~0u, t7, lane)));
            mbar_wait(bars + B_WSP, 0);
            mbar_wait(bars + B_FG, 0);
            uint32_t wd[4], wm[4], vo[32];
            const uint8_t* vp;
            int slot;
            const int kap0 = unit_of(role, 0, slot), al = 2 * kap0;
            const int kap1 = __shfl_sync(~0u, unit_of(role, 1, slot), 0);
            slot = __shfl_sync(~0u, slot, 0);
            cf be1 = twid(kap0 + 512 * q, 2048), be2 = csq(be1), be3 = cmul(be1, be2);
#pragma unroll
            for (int j = 0; j < 4; j++) {
                wd[j] = sb + OFF_WD + ((j + q) & 3) * WPITCH + (al & 15) + 2 * ka + 64 * q;
                wm[j] = sb + OFF_WM + (((role ? 3 : 4) - j - q) & 3) * WPITCH + (-al & 15) + 1024 - 2 * ka - 64 * q;
                wd[j] = __shfl_sync(~0u, wd[j], lane);
            }
#pragma unroll 1
            for (int u = 0; u < nu; u++) {
                const uint32_t buf = sb + OFF_P + u * 16384;
                float acc[64], za[32], zb[32], ya[32], yb[32], vv[64];
                const uint64_t dF = opaque(mkdesc(sb + OFF_F, 16, 1024, 1)), dB = opaque(mkdesc(buf, 4096, 512, 2));
                mbar_wait(bars + B_IN + u * 8, 0);
                STAMP3(22);
                wg_fence();
#pragma unroll
                for (int j = 0; j < 4; j++) mma128_ss<0, 0, 1>(acc, dF + j * 2, dB + j * 64, j);
                wg_commit();
                if (u) {
                    store_unit(vo, vp, role, 0, bars, g_cnt + 64);
                    if (!role) { const uint32_t t = wm[0]; wm[0] = wm[1]; wm[1] = wm[2]; wm[2] = wm[3]; wm[3] = t; }
                }
                STAMP3(39);
                wg_wait<0>();
                pin(acc);
                STAMP3(30);
                uint32_t af[16], ag[16];
#pragma unroll
                for (int b = 0; b < 4; b++) {
                    uint32_t(&o)[16] = b < 2 ? af : ag;
#pragma unroll
                    for (int c = 0; c < 4; c++) {
                        const int i = 4 * (4 * b + c);
                        c2 x = mul2(c2{{acc[i], acc[i + 2]}, {acc[i + 1], acc[i + 3]}}, c2{T[2 * c], T[2 * c + 1]});
                        fin(x);
                        o[4 * c + (b & 1)] = pk(x.a.x, x.a.y);
                        o[4 * c + 2 + (b & 1)] = pk(x.b.x, x.b.y);
                    }
                    if (b & 1) {
                        pinu(o);
                        wg_fence();
#pragma unroll
                        for (int j = 0; j < 4; j++) mma64_rs<0>(b < 2 ? za : zb, o[4 * j], o[4 * j + 1], o[4 * j + 2], o[4 * j + 3], dF + j * 2, j);
                        wg_commit();
                    }
                }
                STAMP3(31);
                mbar_wait(bars + B_WD, u & 1);
                uint32_t wr[16];
#pragma unroll
                for (int i = 0; i < 16; i++) wr[i] = lds16(wd[i >> 2] + 256 * ((i >> 1) & 1) + (i & 1) * 4 * WPITCH);
                wg_wait<0>();
                pin(za);
                pin(zb);
                pinu(af);
                pinu(ag);
                STAMP3(32);
#pragma unroll
                for (int jb = 0; jb < 4; jb++) {
                    const int i = 8 * jb;
                    c2 s0 = {{za[i], za[i + 4]}, {za[i + 1], za[i + 5]}}, s2 = {{za[i + 2], za[i + 6]}, {za[i + 3], za[i + 7]}};
                    c2 s1 = {{zb[i], zb[i + 4]}, {zb[i + 1], zb[i + 5]}}, s3 = {{zb[i + 2], zb[i + 6]}, {zb[i + 3], zb[i + 7]}};
                    s2 = mul2(s2, be1);
                    fin(s2);
                    bfly_tw(s0, s1, be2, s2, s3, be3);
                    bfly(s0, s2); bfly_mi(s1, s3);
                    c2 W[4];
#pragma unroll
                    for (int j = 0; j < 4; j++) {
                        W[j] = {{__uint_as_float(wr[4 * j] << 16), __uint_as_float(wr[4 * j + 1] << 16)}, {__uint_as_float(wr[4 * j + 2] << 16), __uint_as_float(wr[4 * j + 3] << 16)}};
                        if ((jb & 1) == 0)
                            asm volatile("@p0 ld.shared.v2.f32 {%0,%1}, [%2];" : "+f"(W[j].a.x), "+f"(W[j].a.y) : "r"(sb + OFF_WSP + u * 64 + jb * 16 + j * 8));
                    }
                    if (jb < 3) {
#pragma unroll
                        for (int k = 0; k < 16; k++) {
                            const int e = (k >> 1) & 1, pl = (k & 1) * 4 * WPITCH;
                            wr[k] = jb == 0 ? lds16(wd[k >> 2] + 512 + 256 * e + pl) : lds16(wm[k >> 2] - 512 * (jb - 1) - 256 * e + pl);
                        }
                    }
                    if (jb >= 2) {
#pragma unroll
                        for (int j = 0; j < 4; j++) { W[j].a.y = -W[j].a.y; W[j].b.y = -W[j].b.y; }
                    }
                    s0 = mul2(s0, W[0]); fin(s0);
                    s1 = mul2(s1, W[1]); fin(s1);
                    bfly_tw(s0, s2, W[2], s1, s3, W[3]);
                    bfly(s0, s1); bfly_mi(s2, s3);
                    af[4 * jb] = pk(s0.a.x, s0.b.x); af[4 * jb + 1] = pk(s3.a.x, s3.b.x); af[4 * jb + 2] = pk(s0.a.y, s0.b.y); af[4 * jb + 3] = pk(s3.a.y, s3.b.y);
                    ag[4 * jb] = pk(s1.a.x, s1.b.x); ag[4 * jb + 1] = pk(s2.a.x, s2.b.x); ag[4 * jb + 2] = pk(s1.a.y, s1.b.y); ag[4 * jb + 3] = pk(s2.a.y, s2.b.y);
                }
                pinu(af);
                pinu(ag);
                warp_arrive(bars + B_WFREE);
                wg_fence();
#pragma unroll
                for (int j = 0; j < 4; j++) mma64_rs<1>(ya, af[4 * j], af[4 * j + 1], af[4 * j + 2], af[4 * j + 3], dF + j * 128, j);
                wg_commit();
#pragma unroll
                for (int j = 0; j < 4; j++) mma64_rs<1>(yb, ag[4 * j], ag[4 * j + 1], ag[4 * j + 2], ag[4 * j + 3], dF + j * 128, j);
                wg_commit();
                STAMP3(33);
                {
                    const uint32_t a0 = buf + (mi & 1) * 4096 + (16 * w + 8 * (mi >> 1) + gl) * 64 + ((gl >> 1) << 4);
#pragma unroll
                    for (int h = 0; h < 2; h++) {
                        if (h == 0) { wg_wait<1>(); pin(ya); pinu(af); STAMP3(34); } else { wg_wait<0>(); pin(yb); pinu(ag); }
                        const float(&yy)[32] = h ? yb : ya;
#pragma unroll
                        for (int c = 0; c < 4; c++) {
                            const int i = 8 * ((c + 2 * h) & 3), k = 8 * ((c + 2 * h + 1) & 3) + 2;
                            c2 x = {cmulc({yy[i], yy[i + 1]}, T[2 * c]), cmulc({yy[k], yy[k + 1]}, T[2 * c])};
                            fin(x);
                            c2 y = {cmulc({yy[i + 4], yy[i + 5]}, T[2 * c + 1]), cmulc({yy[k + 4], yy[k + 5]}, T[2 * c + 1])};
                            fin(y);
                            stsm4((a0 ^ (c << 4)) + h * 8192, pk(x.a.x, y.a.x), pk(x.b.x, y.b.x), pk(x.a.y, y.a.y), pk(x.b.y, y.b.y));
                        }
                    }
                }
                STAMP3(38);
                fence_async_sm();
                bar_sync(3, 128);
                wg_fence();
#pragma unroll
                for (int j = 0; j < 4; j++) mma128_ss<0, 1, 1>(vv, dF + j * 128, dB + j * 64, j);
                wg_commit();
                STAMP3(35);
                const int lane = fresh_lane(), g = lane >> 2, q = lane & 3;
                vp = padd(g_X + (4 << 20) + w * (8 * 32768) + (role ? u : 1) * 16384 + slot * 64,
                                         (g >> 1) * 32768 + (role ? g & 1 : u) * 32 + (((q ^ (slot >> 1)) & 1) << 4) + (q >> 1) * 8);
                const uint32_t tmask = (((g & 1) == ((slot >> 3) & 1) || !role) && q == ((slot >> 1) & 2)) ? ~1u : ~0u, tbit = ep & ~tmask;
                be1 = twid(kap1 + 512 * q, 2048); be2 = csq(be1); be3 = cmul(be1, be2);
                asm volatile("pmevent 1;" : "+f"(be1.x), "+f"(be1.y), "+f"(be2.x), "+f"(be2.y), "+f"(be3.x), "+f"(be3.y), "+l"(vp)::"memory");
                wg_wait<0>();
                pin(vv);
                STAMP3(36);
#pragma unroll
                for (int k = 0; k < 16; k++) {
                    const int i = 8 * (k >> 1) + 2 * (k & 1);
                    vo[2 * k] = (pk(vv[i], vv[i + 1]) & tmask) | tbit;
                    vo[2 * k + 1] = pk(vv[i + 4], vv[i + 5]);
                }
                pinu(vo);
            }
            store_unit(vo, vp, role, 1, bars, g_cnt + 32 + nu * 32);
        }
        if (spare) return;
        }
        {
            uint32_t sp[8];
            cf tw[8];
            ldtab<2, 2048>(sp, TAB_SP + fb * 4096 + t7 * 16);
            ldtab_cf<16>(tw, TAB_TW3 + fb * 2048 + (t7 >> 2) * 64);
            const uint64_t dF = opaque(mkdesc(sb + OFF_F, 16, 1024, 1)), dB = opaque(mkdesc(sb + OFF_P + hf * 8192, 1024, 256, 3));
            const uint8_t* op = padd(p.out + (1024 + fb) * 2048 + fcb * 32 + hf * 16, (t7 >> 2) * 32768 + (q >> 1) * 16 + (q & 1) * 32);
            float acc[64], out[64];
            mbar_wait(bars + B_IN + 24, 0);
            mbar_wait(bars + B_FG, 1);
            STAMP(25);
            pinu(sp);
            wg_fence();
#pragma unroll
            for (int j = 0; j < 4; j++) {
                const uint64_t db = dB + (j >> 1) * 1024 + (j & 1) * 32;
                mma112_ss(acc, dF + j * 2, db + 64, j);
                if (j & 1) mma16_rs(acc, 0u, sp[2 * j], 0u, sp[2 * j + 1], db, 1);
                else mma16_rs(acc, sp[2 * j], 0u, sp[2 * j + 1], 0u, db, j);
            }
            wg_commit();
            wg_wait<0>();
            pin(acc);
            pinu(sp);
            warp_arrive(bars + B_P3M);
#pragma unroll
            for (int cl = 0; cl < 2; cl++) {
                c2 z[8];
#pragma unroll
                for (int n = 0; n < 8; n++) {
                    const int i = 4 * (2 * n + cl);
                    z[n] = {{acc[i], acc[i + 2]}, {acc[i + 1], acc[i + 3]}};
                }
                z[0] = {{z[0].a.x + z[0].a.y, z[0].a.x - z[0].a.y}, {z[0].b.x + z[0].b.y, z[0].b.x - z[0].b.y}};
                z[4] = mul2(z[4], tw[4]);
                fin(z[0], z[4]);
#pragma unroll
                for (int n = 1; n < 4; n++) {
                    const cf iw = n == 1 ? cf{0.38268343236508977f, 0.92387953251128674f}
                                         : (n == 2 ? cf{0.70710678118654752f, 0.70710678118654752f} : cf{0.92387953251128674f, 0.38268343236508977f});
                    c2 y = mul2(z[n], tw[n]);
                    fin(y);
                    const cf t = {tw[8 - n].x, -tw[8 - n].y};
                    c2 E = fma2(c2{{z[8 - n].a.x, -z[8 - n].a.y}, {z[8 - n].b.x, -z[8 - n].b.y}}, t, y);
                    fin(E);
                    z[n] = fma2(twm2(y, E), iw, E);
                    fin(z[n]);
                    z[8 - n] = {{fmaf(2.f, E.a.x, -z[n].a.x), fmaf(-2.f, E.a.y, z[n].a.y)}, {fmaf(2.f, E.b.x, -z[n].b.x), fmaf(-2.f, E.b.y, z[n].b.y)}};
                }
                dft8<false>(z, tw);
#pragma unroll
                for (int m = 0; m < 8; m++) {
                    out[8 * m + 2 * cl] = z[m].a.x; out[8 * m + 2 * cl + 1] = z[m].b.x;
                    out[8 * m + 4 + 2 * cl] = z[m].a.y; out[8 * m + 5 + 2 * cl] = z[m].b.y;
                }
            }
            STAMP(26);
#pragma unroll
            for (int m = 0; m < 16; m++) {
                asm volatile("st.global.v4.f32 [%0], {%1,%2,%3,%4};" ::"l"(op + (m - 8) * (1 << 20)), "f"(out[4 * m]), "f"(out[4 * m + 1]), "f"(out[4 * m + 2]), "f"(out[4 * m + 3]) : "memory");
                if (PACE_O && m < 15 && m % PACE_ON == PACE_ON - 1)
                    asm volatile("{.reg .pred p; mbarrier.test_wait.parity.shared::cta.b64 p, [%0], 0; @!p nanosleep.u32 %1;}" ::"r"(bars + B_DONE), "n"(PACE_O) : "memory");
            }
            STAMP(27);
        }
    }
}

typedef CUresult (*EncodeFn)(CUtensorMap*, CUtensorMapDataType, cuuint32_t, void*, const cuuint64_t*, const cuuint64_t*, const cuuint32_t*,
                             const cuuint32_t*, CUtensorMapInterleave, CUtensorMapSwizzle, CUtensorMapL2promotion, CUtensorMapFloatOOBfill);

static CUtensorMap make_map(EncodeFn enc, const void* ptr, int rank, const cuuint64_t* dims, const cuuint64_t* strides, const cuuint32_t* box,
                            CUtensorMapSwizzle swz, CUtensorMapL2promotion promo, CUtensorMapDataType dt = CU_TENSOR_MAP_DATA_TYPE_BFLOAT16) {
    CUtensorMap m;
    const cuuint32_t es[5] = {1, 1, 1, 1, 1};
    enc(&m, dt, rank, const_cast<void*>(ptr), dims, strides, box, es, CU_TENSOR_MAP_INTERLEAVE_NONE, swz, promo,
        CU_TENSOR_MAP_FLOAT_OOB_FILL_NONE);
    return m;
}

extern "C" void kernel_launch(void* const* d_in, const int* in_sizes, int n_in, void* d_out, int out_size) {
    void* fn = nullptr;
    cudaDriverEntryPointQueryResult qr;
    cudaGetDriverEntryPoint("cuTensorMapEncodeTiled", &fn, cudaEnableDefault, &qr);
    EncodeFn enc = (EncodeFn)fn;
    void* pX;
    cudaGetSymbolAddress(&pX, g_X);
    const CUtensorMapL2promotion P256 = CU_TENSOR_MAP_L2_PROMOTION_L2_256B, P0 = CU_TENSOR_MAP_L2_PROMOTION_NONE;

    const cuuint64_t dX[5] = {1024, 2, 4, 16, 16}, sX[4] = {2048, 32 * 2048, 2 * 2048, 128 * 2048};
    const cuuint32_t bX[5] = {64, 2, 4, 16, 1};
    CUtensorMap tmX = make_map(enc, d_in[3], 5, dX, sX, bX, CU_TENSOR_MAP_SWIZZLE_128B, P256);
    const cuuint64_t dXd[4] = {64, 2048, 2, 16}, sXd[3] = {2048, 64 * 2048, 128};
    const cuuint32_t bXd[4] = {64, 16, 2, 2};
    CUtensorMap tmXd = make_map(enc, d_in[3], 4, dXd, sXd, bXd, CU_TENSOR_MAP_SWIZZLE_128B, P256);
    const cuuint64_t dB[4] = {1024, 8, 4, 32}, sB[3] = {2048, 256 * 2048, 8 * 2048};
    const cuuint32_t bB4[4] = {64, 8, 2, 4};
    CUtensorMap tmBre = make_map(enc, d_in[6], 4, dB, sB, bB4, CU_TENSOR_MAP_SWIZZLE_128B, P256);
    CUtensorMap tmBim = make_map(enc, d_in[7], 4, dB, sB, bB4, CU_TENSOR_MAP_SWIZZLE_128B, P256);
    const cuuint64_t dC[5] = {1024, 2, 4, 2, 64}, sC[4] = {2048, 4 * 2048, 2 * 2048, 16 * 2048};
    const cuuint32_t bC[5] = {64, 2, 4, 2, 4};
    CUtensorMap tmCre = make_map(enc, d_in[8], 5, dC, sC, bC, CU_TENSOR_MAP_SWIZZLE_128B, P256);
    CUtensorMap tmCim = make_map(enc, d_in[9], 5, dC, sC, bC, CU_TENSOR_MAP_SWIZZLE_128B, P256);

    const cuuint64_t dU[2] = {8192, 256}, sU[1] = {16384};
    const cuuint32_t bU[2] = {64, 64};
    CUtensorMap tmUst = make_map(enc, pX, 2, dU, sU, bU, CU_TENSOR_MAP_SWIZZLE_128B, P0);
    const cuuint64_t dF[2] = {512 * 1026 / 8, 4}, sF[1] = {512 * 1026};
    const cuuint32_t bF[2] = {WPITCH / 8, 4};
    CUtensorMap tmWr = make_map(enc, d_in[1], 2, dF, sF, bF, CU_TENSOR_MAP_SWIZZLE_NONE, P0, CU_TENSOR_MAP_DATA_TYPE_UINT64);
    CUtensorMap tmWi = make_map(enc, d_in[2], 2, dF, sF, bF, CU_TENSOR_MAP_SWIZZLE_NONE, P0, CU_TENSOR_MAP_DATA_TYPE_UINT64);

    const cuuint64_t dA[3] = {1024, 64, 32}, sA[2] = {32 * 2048, 2048};
    const cuuint32_t bA[3] = {32, 64, 1};
    CUtensorMap tmXa = make_map(enc, d_in[0], 3, dA, sA, bA, CU_TENSOR_MAP_SWIZZLE_64B, XA_PROMO);

    Params p;
    p.wr = (const __nv_bfloat16*)d_in[1];
    p.wi = (const __nv_bfloat16*)d_in[2];
    p.lre = (const __nv_bfloat16*)d_in[4];
    p.lim = (const __nv_bfloat16*)d_in[5];
    p.ldt = (const __nv_bfloat16*)d_in[10];
    p.dsk = (const __nv_bfloat16*)d_in[11];
    p.out = (float*)d_out;
    int dev = 0, sms = 0;
    cudaGetDevice(&dev);
    cudaDeviceGetAttribute(&sms, cudaDevAttrMultiProcessorCount, dev);
    auto kernel = sms == 132 ? fused_kernel<true> : fused_kernel<false>;
    cudaFuncSetAttribute(kernel, cudaFuncAttributeMaxDynamicSharedMemorySize, SMEM_BYTES);
    kernel<<<132, 512, SMEM_BYTES>>>(tmX, tmBre, tmBim, tmCre, tmCim, tmXd, tmUst, tmWr, tmWi, tmXa, p);
}
```

```cpp
#include <cuda_runtime.h>
#include <cuda.h>
#include <cuda_bf16.h>
#include <stdint.h>

#define NST 5
#define WPITCH 1056
#define OFF_P (NST * 32768)
#define OFF_F (OFF_P + 32768)
#define OFF_WD (OFF_F + 8192)
#define OFF_WM (OFF_WD + 8 * WPITCH)
#define OFF_BAR (OFF_F + 32768)
#define OFF_LAM (OFF_BAR + 432)
#define OFF_WSP (OFF_LAM + 2048)
#define OFF_PROF (OFF_WSP + 128)
#define SMEM_BYTES OFF_PROF
#define B_FULL 0
#define B_HL 40
#define B_EP 120
#define B_HR 128
#define B_XD 144
#define B_FG 160
#define B_WSP 168
#define B_WD 176
#define B_DONE 184
#define B_LD 192
#define B_RAW 200
#define B_LAM 208
#define B_IN 216
#define B_XIN 248
#define B_EMPTY 256
#define B_STG 320
#define B_WFREE 328
#define B_HOWN 336
#define B_STGU 368
#define B_P3M 384
#define B_EPOCH 416

#define PACE_U 20
#define PACE_V 20
#define XA_PACE 200
#define XA_PACE2 100
#define XA_TAB 0
#define XA_TABP 200
#define PACE_O 200
#define PACE_ON 1
#define XA_PROMO CU_TENSOR_MAP_L2_PROMOTION_L2_128B
#define TAB_T0 500
#define LAM_T0 1000
#define DEFER 0
#define UHINT 1
#define VPOS 2
#define VPOS0 8
#define GOV_T 100
#define GOV_K0 16
#define GOV_N 22
#define TIDMAP threadIdx.x
#define U1POS 2
#define WPFB B_XIN
#define VS0 16
#define XA_N0 2
#define XA_T0 0
#define PACE_X 200
#define SKEW 4
#define SPIN_LIMIT (1u << 15)

__device__ __align__(1024) uint8_t g_X[8 << 20];
__device__ __align__(1024) uint8_t g_H[8 << 20];
__device__ __align__(1024) uint4 g_carry[16 * 512];
__device__ __align__(128) unsigned g_cnt[128];
__device__ __align__(128) unsigned g_epoch[132 * 8];

#define STAMP(i) do { } while (0)
#define STAMPO(i, o) do { } while (0)
#define STAMPW(a, b) do { } while (0)
#define STAMPX(a, b) do { } while (0)
#define STAMP5(i) do { } while (0)
#define STAMP6(i) do { } while (0)
#define STAMP3(i) do { } while (0)

#define TAB_FG 0
#define TAB_G 8192
#define TAB_F1 40960
#define TAB_T 49152
#define TAB_SP 57344
#define TAB_TW1 73728
#define TAB_TW3 75776
#define TAB_PC 83968
__device__ __align__(1024) const uint32_t g_tab[21248] = {
0x80003d80,0x80003d80,0x80003d80,0x80003d80,0x80003d80,0x80003d80,0x80003d80,0x80003d80,0x80003d80,0x80003d80,0x80003d80,0x80003d80,0x80003d80,0x80003d80,0x80003d80,0x80003d80,
0x80003d80,0x80003d80,0x80003d80,0x80003d80,0x80003d80,0x80003d80,0x80003d80,0x80003d80,0x80003d80,0x80003d80,0x80003d80,0x80003d80,0x80003d80,0x80003d80,0x80003d80,0x80003d80,
0x3d353d35,0x3d35bd35,0xbd35bd35,0xbd353d35,0x80003d80,0x3d800000,0x8000bd80,0xbd800000,0x3d353d35,0x3d35bd35,0xbd35bd35,0xbd353d35,0x80003d80,0x3d800000,0x8000bd80,0xbd800000,
0x3d353d35,0x3d35bd35,0xbd35bd35,0xbd353d35,0x80003d80,0x3d800000,0x8000bd80,0xbd800000,0x3d353d35,0x3d35bd35,0xbd35bd35,0xbd353d35,0x80003d80,0x3d800000,0x8000bd80,0xbd800000,
0x3d800000,0x3d6dbcc4,0x3d35bd35,0x3cc4bd6d,0x3d7bbc48,0x3d55bd0e,0x3d0ebd55,0x3c48bd7b,0x80003d80,0x3cc43d6d,0x3d353d35,0x3d6d3cc4,0x3c483d7b,0x3d0e3d55,0x3d553d0e,0x3d7b3c48,
0xbd800000,0xbd6d3cc4,0xbd353d35,0xbcc43d6d,0xbd7b3c48,0xbd553d0e,0xbd0e3d55,0xbc483d7b,0x8000bd80,0xbcc4bd6d,0xbd35bd35,0xbd6dbcc4,0xbc48bd7b,0xbd0ebd55,0xbd55bd0e,0xbd7bbc48,
0x3d0ebd55,0xbd7bbc48,0x3c483d7b,0x3d55bd0e,0x3d800000,0xbcc4bd6d,0xbd353d35,0x3d6d3cc4,0x3d553d0e,0x3c48bd7b,0xbd7b3c48,0x3d0e3d55,0x80003d80,0x3d6dbcc4,0xbd35bd35,0xbcc43d6d,
0xbd0e3d55,0x3d7b3c48,0xbc48bd7b,0xbd553d0e,0xbd800000,0x3cc43d6d,0x3d35bd35,0xbd6dbcc4,0xbd55bd0e,0xbc483d7b,0x3d7bbc48,0xbd0ebd55,0x8000bd80,0xbd6d3cc4,0x3d353d35,0x3cc4bd6d,
0x80003d80,0x3d353d35,0x3d800000,0x3d35bd35,0x3cc43d6d,0x3d6d3cc4,0x3d6dbcc4,0x3cc4bd6d,0x8000bd80,0xbd35bd35,0xbd800000,0xbd353d35,0xbcc4bd6d,0xbd6dbcc4,0xbd6d3cc4,0xbcc43d6d,
0x80003d80,0x3d353d35,0x3d800000,0x3d35bd35,0x3cc43d6d,0x3d6d3cc4,0x3d6dbcc4,0x3cc4bd6d,0x8000bd80,0xbd35bd35,0xbd800000,0xbd353d35,0xbcc4bd6d,0xbd6dbcc4,0xbd6d3cc4,0xbcc43d6d,
0x3d6d3cc4,0xbcc4bd6d,0xbcc43d6d,0x3d6dbcc4,0x80003d80,0x3d35bd35,0xbd800000,0x3d353d35,0xbd6dbcc4,0x3cc43d6d,0x3cc4bd6d,0xbd6d3cc4,0x8000bd80,0xbd353d35,0x3d800000,0xbd35bd35,
0x3d6d3cc4,0xbcc4bd6d,0xbcc43d6d,0x3d6dbcc4,0x80003d80,0x3d35bd35,0xbd800000,0x3d353d35,0xbd6dbcc4,0x3cc43d6d,0x3cc4bd6d,0xbd6d3cc4,0x8000bd80,0xbd353d35,0x3d800000,0xbd35bd35,
0x3d800000,0x3cc4bd6d,0xbd35bd35,0xbd6d3cc4,0x3d55bd0e,0xbc48bd7b,0xbd7bbc48,0xbd0e3d55,0x8000bd80,0xbd6dbcc4,0xbd353d35,0x3cc43d6d,0xbd0ebd55,0xbd7b3c48,0xbc483d7b,0x3d553d0e,
0xbd800000,0xbcc43d6d,0x3d353d35,0x3d6dbcc4,0xbd553d0e,0x3c483d7b,0x3d7b3c48,0x3d0ebd55,0x80003d80,0x3d6d3cc4,0x3d35bd35,0xbcc4bd6d,0x3d0e3d55,0x3d7bbc48,0x3c48bd7b,0xbd55bd0e,
0x3c48bd7b,0xbd0e3d55,0x3d55bd0e,0xbd7b3c48,0x3d800000,0xbd6dbcc4,0x3d353d35,0xbcc4bd6d,0xbd7bbc48,0x3d553d0e,0xbd0ebd55,0x3c483d7b,0x8000bd80,0xbcc43d6d,0x3d35bd35,0xbd6d3cc4,
0xbc483d7b,0x3d0ebd55,0xbd553d0e,0x3d7bbc48,0xbd800000,0x3d6d3cc4,0xbd35bd35,0x3cc43d6d,0x3d7b3c48,0xbd55bd0e,0x3d0e3d55,0xbc48bd7b,0x80003d80,0x3cc4bd6d,0xbd353d35,0x3d6dbcc4,
0x3d800000,0x3d800000,0x3d800000,0x3d800000,0x3d800000,0x3d800000,0x3d800000,0x3d800000,0x3d800000,0x3d800000,0x3d800000,0x3d800000,0x3d800000,0x3d800000,0x3d800000,0x3d800000,
0x3d800000,0x3d800000,0x3d800000,0x3d800000,0x3d800000,0x3d800000,0x3d800000,0x3d800000,0x3d800000,0x3d800000,0x3d800000,0x3d800000,0x3d800000,0x3d800000,0x3d800000,0x3d800000,
0x3d35bd35,0xbd35bd35,0xbd353d35,0x3d353d35,0x3d800000,0xbd80,0xbd800000,0x3d80,0x3d35bd35,0xbd35bd35,0xbd353d35,0x3d353d35,0x3d800000,0xbd80,0xbd800000,0x3d80,
0x3d35bd35,0xbd35bd35,0xbd353d35,0x3d353d35,0x3d800000,0xbd80,0xbd800000,0x3d80,0x3d35bd35,0xbd35bd35,0xbd353d35,0x3d353d35,0x3d800000,0xbd80,0xbd800000,0x3d80,
0xbd80,0xbcc4bd6d,0xbd35bd35,0xbd6dbcc4,0xbc48bd7b,0xbd0ebd55,0xbd55bd0e,0xbd7bbc48,0x3d800000,0x3d6dbcc4,0x3d35bd35,0x3cc4bd6d,0x3d7bbc48,0x3d55bd0e,0x3d0ebd55,0x3c48bd7b,
0x3d80,0x3cc43d6d,0x3d353d35,0x3d6d3cc4,0x3c483d7b,0x3d0e3d55,0x3d553d0e,0x3d7b3c48,0xbd800000,0xbd6d3cc4,0xbd353d35,0xbcc43d6d,0xbd7b3c48,0xbd553d0e,0xbd0e3d55,0xbc483d7b,
0xbd55bd0e,0xbc483d7b,0x3d7bbc48,0xbd0ebd55,0xbd80,0xbd6d3cc4,0x3d353d35,0x3cc4bd6d,0x3d0ebd55,0xbd7bbc48,0x3c483d7b,0x3d55bd0e,0x3d800000,0xbcc4bd6d,0xbd353d35,0x3d6d3cc4,
0x3d553d0e,0x3c48bd7b,0xbd7b3c48,0x3d0e3d55,0x3d80,0x3d6dbcc4,0xbd35bd35,0xbcc43d6d,0xbd0e3d55,0x3d7b3c48,0xbc48bd7b,0xbd553d0e,0xbd800000,0x3cc43d6d,0x3d35bd35,0xbd6dbcc4,
0x3d800000,0x3d35bd35,0xbd80,0xbd35bd35,0x3d6dbcc4,0x3cc4bd6d,0xbcc4bd6d,0xbd6dbcc4,0xbd800000,0xbd353d35,0x3d80,0x3d353d35,0xbd6d3cc4,0xbcc43d6d,0x3cc43d6d,0x3d6d3cc4,
0x3d800000,0x3d35bd35,0xbd80,0xbd35bd35,0x3d6dbcc4,0x3cc4bd6d,0xbcc4bd6d,0xbd6dbcc4,0xbd800000,0xbd353d35,0x3d80,0x3d353d35,0xbd6d3cc4,0xbcc43d6d,0x3cc43d6d,0x3d6d3cc4,
0x3cc4bd6d,0xbd6d3cc4,0x3d6d3cc4,0xbcc4bd6d,0x3d800000,0xbd35bd35,0x3d80,0x3d35bd35,0xbcc43d6d,0x3d6dbcc4,0xbd6dbcc4,0x3cc43d6d,0xbd800000,0x3d353d35,0xbd80,0xbd353d35,
0x3cc4bd6d,0xbd6d3cc4,0x3d6d3cc4,0xbcc4bd6d,0x3d800000,0xbd35bd35,0x3d80,0x3d35bd35,0xbcc43d6d,0x3d6dbcc4,0xbd6dbcc4,0x3cc43d6d,0xbd800000,0x3d353d35,0xbd80,0xbd353d35,
0xbd80,0xbd6dbcc4,0xbd353d35,0x3cc43d6d,0xbd0ebd55,0xbd7b3c48,0xbc483d7b,0x3d553d0e,0xbd800000,0xbcc43d6d,0x3d353d35,0x3d6dbcc4,0xbd553d0e,0x3c483d7b,0x3d7b3c48,0x3d0ebd55,
0x3d80,0x3d6d3cc4,0x3d35bd35,0xbcc4bd6d,0x3d0e3d55,0x3d7bbc48,0x3c48bd7b,0xbd55bd0e,0x3d800000,0x3cc4bd6d,0xbd35bd35,0xbd6d3cc4,0x3d55bd0e,0xbc48bd7b,0xbd7bbc48,0xbd0e3d55,
0xbd7bbc48,0x3d553d0e,0xbd0ebd55,0x3c483d7b,0xbd80,0xbcc43d6d,0x3d35bd35,0xbd6d3cc4,0xbc483d7b,0x3d0ebd55,0xbd553d0e,0x3d7bbc48,0xbd800000,0x3d6d3cc4,0xbd35bd35,0x3cc43d6d,
0x3d7b3c48,0xbd55bd0e,0x3d0e3d55,0xbc48bd7b,0x3d80,0x3cc4bd6d,0xbd353d35,0x3d6dbcc4,0x3c48bd7b,0xbd0e3d55,0x3d55bd0e,0xbd7b3c48,0x3d800000,0xbd6dbcc4,0x3d353d35,0xbcc4bd6d,
0x80003d80,0x8000bd80,0x80003d80,0x8000bd80,0x3d800000,0xbd800000,0x3d800000,0xbd800000,0x80003d80,0x8000bd80,0x80003d80,0x8000bd80,0x3d800000,0xbd800000,0x3d800000,0xbd800000,
0x80003d80,0x8000bd80,0x80003d80,0x8000bd80,0x3d800000,0xbd800000,0x3d800000,0xbd800000,0x80003d80,0x8000bd80,0x80003d80,0x8000bd80,0x3d800000,0xbd800000,0x3d800000,0xbd800000,
0x3d35bd35,0x3d353d35,0xbd353d35,0xbd35bd35,0x80003d80,0xbd800000,0x8000bd80,0x3d800000,0x3d35bd35,0x3d353d35,0xbd353d35,0xbd35bd35,0x80003d80,0xbd800000,0x8000bd80,0x3d800000,
0x3d35bd35,0x3d353d35,0xbd353d35,0xbd35bd35,0x80003d80,0xbd800000,0x8000bd80,0x3d800000,0x3d35bd35,0x3d353d35,0xbd353d35,0xbd35bd35,0x80003d80,0xbd800000,0x8000bd80,0x3d800000,
0x3d800000,0xbd6d3cc4,0x3d35bd35,0xbcc43d6d,0xbc48bd7b,0x3d0e3d55,0xbd55bd0e,0x3d7b3c48,0x80003d80,0xbcc4bd6d,0x3d353d35,0xbd6dbcc4,0x3d7bbc48,0xbd553d0e,0x3d0ebd55,0xbc483d7b,
0xbd800000,0x3d6dbcc4,0xbd353d35,0x3cc4bd6d,0x3c483d7b,0xbd0ebd55,0x3d553d0e,0xbd7bbc48,0x8000bd80,0x3cc43d6d,0xbd35bd35,0x3d6d3cc4,0xbd7b3c48,0x3d55bd0e,0xbd0e3d55,0x3c48bd7b,
0xbd55bd0e,0x3c48bd7b,0x3d7bbc48,0x3d0e3d55,0x3d800000,0x3cc43d6d,0xbd353d35,0xbd6dbcc4,0x3d0ebd55,0x3d7b3c48,0x3c483d7b,0xbd553d0e,0x80003d80,0xbd6d3cc4,0xbd35bd35,0x3cc4bd6d,
0x3d553d0e,0xbc483d7b,0xbd7b3c48,0xbd0ebd55,0xbd800000,0xbcc4bd6d,0x3d35bd35,0x3d6d3cc4,0xbd0e3d55,0xbd7bbc48,0xbc48bd7b,0x3d55bd0e,0x8000bd80,0x3d6dbcc4,0x3d353d35,0xbcc43d6d,
0x80003d80,0xbd35bd35,0x3d800000,0xbd353d35,0x3d6dbcc4,0xbcc43d6d,0xbcc4bd6d,0x3d6d3cc4,0x8000bd80,0x3d353d35,0xbd800000,0x3d35bd35,0xbd6d3cc4,0x3cc4bd6d,0x3cc43d6d,0xbd6dbcc4,
0x80003d80,0xbd35bd35,0x3d800000,0xbd353d35,0x3d6dbcc4,0xbcc43d6d,0xbcc4bd6d,0x3d6d3cc4,0x8000bd80,0x3d353d35,0xbd800000,0x3d35bd35,0xbd6d3cc4,0x3cc4bd6d,0x3cc43d6d,0xbd6dbcc4,
0x3cc4bd6d,0x3d6dbcc4,0x3d6d3cc4,0x3cc43d6d,0x80003d80,0xbd353d35,0xbd800000,0xbd35bd35,0xbcc43d6d,0xbd6d3cc4,0xbd6dbcc4,0xbcc4bd6d,0x8000bd80,0x3d35bd35,0x3d800000,0x3d353d35,
0x3cc4bd6d,0x3d6dbcc4,0x3d6d3cc4,0x3cc43d6d,0x80003d80,0xbd353d35,0xbd800000,0xbd35bd35,0xbcc43d6d,0xbd6d3cc4,0xbd6dbcc4,0xbcc4bd6d,0x8000bd80,0x3d35bd35,0x3d800000,0x3d353d35,
0x3d800000,0xbcc43d6d,0xbd35bd35,0x3d6dbcc4,0xbd0ebd55,0x3d7bbc48,0xbc483d7b,0xbd55bd0e,0x8000bd80,0x3d6d3cc4,0xbd353d35,0xbcc4bd6d,0xbd553d0e,0xbc48bd7b,0x3d7b3c48,0xbd0e3d55,
0xbd800000,0x3cc4bd6d,0x3d353d35,0xbd6d3cc4,0x3d0e3d55,0xbd7b3c48,0x3c48bd7b,0x3d553d0e,0x80003d80,0xbd6dbcc4,0x3d35bd35,0x3cc43d6d,0x3d55bd0e,0x3c483d7b,0xbd7bbc48,0x3d0ebd55,
0xbd7bbc48,0xbd55bd0e,0xbd0ebd55,0xbc48bd7b,0x3d800000,0x3d6d3cc4,0x3d353d35,0x3cc43d6d,0xbc483d7b,0xbd0e3d55,0xbd553d0e,0xbd7b3c48,0x8000bd80,0x3cc4bd6d,0x3d35bd35,0x3d6dbcc4,
0x3d7b3c48,0x3d553d0e,0x3d0e3d55,0x3c483d7b,0xbd800000,0xbd6dbcc4,0xbd35bd35,0xbcc4bd6d,0x3c48bd7b,0x3d0ebd55,0x3d55bd0e,0x3d7bbc48,0x80003d80,0xbcc43d6d,0xbd353d35,0xbd6d3cc4,
0x3d800000,0xbd800000,0x3d800000,0xbd800000,0xbd80,0x3d80,0xbd80,0x3d80,0x3d800000,0xbd800000,0x3d800000,0xbd800000,0xbd80,0x3d80,0xbd80,0x3d80,
0x3d800000,0xbd800000,0x3d800000,0xbd800000,0xbd80,0x3d80,0xbd80,0x3d80,0x3d800000,0xbd800000,0x3d800000,0xbd800000,0xbd80,0x3d80,0xbd80,0x3d80,
0xbd35bd35,0x3d35bd35,0x3d353d35,0xbd353d35,0x3d800000,0x3d80,0xbd800000,0xbd80,0xbd35bd35,0x3d35bd35,0x3d353d35,0xbd353d35,0x3d800000,0x3d80,0xbd800000,0xbd80,
0xbd35bd35,0x3d35bd35,0x3d353d35,0xbd353d35,0x3d800000,0x3d80,0xbd800000,0xbd80,0xbd35bd35,0x3d35bd35,0x3d353d35,0xbd353d35,0x3d800000,0x3d80,0xbd800000,0xbd80,
0xbd80,0x3cc43d6d,0xbd35bd35,0x3d6d3cc4,0xbd7b3c48,0x3d55bd0e,0xbd0e3d55,0x3c48bd7b,0x3d800000,0xbd6d3cc4,0x3d35bd35,0xbcc43d6d,0xbc48bd7b,0x3d0e3d55,0xbd55bd0e,0x3d7b3c48,
0x3d80,0xbcc4bd6d,0x3d353d35,0xbd6dbcc4,0x3d7bbc48,0xbd553d0e,0x3d0ebd55,0xbc483d7b,0xbd800000,0x3d6dbcc4,0xbd353d35,0x3cc4bd6d,0x3c483d7b,0xbd0ebd55,0x3d553d0e,0xbd7bbc48,
0xbd0e3d55,0xbd7bbc48,0xbc48bd7b,0x3d55bd0e,0xbd80,0x3d6dbcc4,0x3d353d35,0xbcc43d6d,0xbd55bd0e,0x3c48bd7b,0x3d7bbc48,0x3d0e3d55,0x3d800000,0x3cc43d6d,0xbd353d35,0xbd6dbcc4,
0x3d0ebd55,0x3d7b3c48,0x3c483d7b,0xbd553d0e,0x3d80,0xbd6d3cc4,0xbd35bd35,0x3cc4bd6d,0x3d553d0e,0xbc483d7b,0xbd7b3c48,0xbd0ebd55,0xbd800000,0xbcc4bd6d,0x3d35bd35,0x3d6d3cc4,
0x3d800000,0xbd353d35,0xbd80,0x3d353d35,0xbcc4bd6d,0x3d6d3cc4,0xbd6d3cc4,0x3cc4bd6d,0xbd800000,0x3d35bd35,0x3d80,0xbd35bd35,0x3cc43d6d,0xbd6dbcc4,0x3d6dbcc4,0xbcc43d6d,
0x3d800000,0xbd353d35,0xbd80,0x3d353d35,0xbcc4bd6d,0x3d6d3cc4,0xbd6d3cc4,0x3cc4bd6d,0xbd800000,0x3d35bd35,0x3d80,0xbd35bd35,0x3cc43d6d,0xbd6dbcc4,0x3d6dbcc4,0xbcc43d6d,
0xbd6dbcc4,0xbcc4bd6d,0x3cc4bd6d,0x3d6dbcc4,0x3d800000,0x3d353d35,0x3d80,0xbd353d35,0x3d6d3cc4,0x3cc43d6d,0xbcc43d6d,0xbd6d3cc4,0xbd800000,0xbd35bd35,0xbd80,0x3d35bd35,
0xbd6dbcc4,0xbcc4bd6d,0x3cc4bd6d,0x3d6dbcc4,0x3d800000,0x3d353d35,0x3d80,0xbd353d35,0x3d6d3cc4,0x3cc43d6d,0xbcc43d6d,0xbd6d3cc4,0xbd800000,0xbd35bd35,0xbd80,0x3d35bd35,
0xbd80,0x3d6d3cc4,0xbd353d35,0xbcc4bd6d,0xbd553d0e,0xbc48bd7b,0x3d7b3c48,0xbd0e3d55,0xbd800000,0x3cc4bd6d,0x3d353d35,0xbd6d3cc4,0x3d0e3d55,0xbd7b3c48,0x3c48bd7b,0x3d553d0e,
0x3d80,0xbd6dbcc4,0x3d35bd35,0x3cc43d6d,0x3d55bd0e,0x3c483d7b,0xbd7bbc48,0x3d0ebd55,0x3d800000,0xbcc43d6d,0xbd35bd35,0x3d6dbcc4,0xbd0ebd55,0x3d7bbc48,0xbc483d7b,0xbd55bd0e,
0xbc483d7b,0xbd0e3d55,0xbd553d0e,0xbd7b3c48,0xbd80,0x3cc4bd6d,0x3d35bd35,0x3d6dbcc4,0x3d7b3c48,0x3d553d0e,0x3d0e3d55,0x3c483d7b,0xbd800000,0xbd6dbcc4,0xbd35bd35,0xbcc4bd6d,
0x3c48bd7b,0x3d0ebd55,0x3d55bd0e,0x3d7bbc48,0x3d80,0xbcc43d6d,0xbd353d35,0xbd6d3cc4,0xbd7bbc48,0xbd55bd0e,0xbd0ebd55,0xbc48bd7b,0x3d800000,0x3d6d3cc4,0x3d353d35,0x3cc43d6d,
0x80003d80,0x80003d80,0x80003d80,0x80003d80,0x8000bd80,0x8000bd80,0x8000bd80,0x8000bd80,0x80003d80,0x80003d80,0x80003d80,0x80003d80,0x8000bd80,0x8000bd80,0x8000bd80,0x8000bd80,
0x80003d80,0x80003d80,0x80003d80,0x80003d80,0x8000bd80,0x8000bd80,0x8000bd80,0x8000bd80,0x80003d80,0x80003d80,0x80003d80,0x80003d80,0x8000bd80,0x8000bd80,0x8000bd80,0x8000bd80,
0xbd35bd35,0xbd353d35,0x3d353d35,0x3d35bd35,0x80003d80,0x3d800000,0x8000bd80,0xbd800000,0xbd35bd35,0xbd353d35,0x3d353d35,0x3d35bd35,0x80003d80,0x3d800000,0x8000bd80,0xbd800000,
0xbd35bd35,0xbd353d35,0x3d353d35,0x3d35bd35,0x80003d80,0x3d800000,0x8000bd80,0xbd800000,0xbd35bd35,0xbd353d35,0x3d353d35,0x3d35bd35,0x80003d80,0x3d800000,0x8000bd80,0xbd800000,
0x3d800000,0x3d6dbcc4,0x3d35bd35,0x3cc4bd6d,0xbd7b3c48,0xbd553d0e,0xbd0e3d55,0xbc483d7b,0x80003d80,0x3cc43d6d,0x3d353d35,0x3d6d3cc4,0xbc48bd7b,0xbd0ebd55,0xbd55bd0e,0xbd7bbc48,
0xbd800000,0xbd6d3cc4,0xbd353d35,0xbcc43d6d,0x3d7bbc48,0x3d55bd0e,0x3d0ebd55,0x3c48bd7b,0x8000bd80,0xbcc4bd6d,0xbd35bd35,0xbd6dbcc4,0x3c483d7b,0x3d0e3d55,0x3d553d0e,0x3d7b3c48,
0xbd0e3d55,0x3d7b3c48,0xbc48bd7b,0xbd553d0e,0x3d800000,0xbcc4bd6d,0xbd353d35,0x3d6d3cc4,0xbd55bd0e,0xbc483d7b,0x3d7bbc48,0xbd0ebd55,0x80003d80,0x3d6dbcc4,0xbd35bd35,0xbcc43d6d,
0x3d0ebd55,0xbd7bbc48,0x3c483d7b,0x3d55bd0e,0xbd800000,0x3cc43d6d,0x3d35bd35,0xbd6dbcc4,0x3d553d0e,0x3c48bd7b,0xbd7b3c48,0x3d0e3d55,0x8000bd80,0xbd6d3cc4,0x3d353d35,0x3cc4bd6d,
0x80003d80,0x3d353d35,0x3d800000,0x3d35bd35,0xbcc4bd6d,0xbd6dbcc4,0xbd6d3cc4,0xbcc43d6d,0x8000bd80,0xbd35bd35,0xbd800000,0xbd353d35,0x3cc43d6d,0x3d6d3cc4,0x3d6dbcc4,0x3cc4bd6d,
0x80003d80,0x3d353d35,0x3d800000,0x3d35bd35,0xbcc4bd6d,0xbd6dbcc4,0xbd6d3cc4,0xbcc43d6d,0x8000bd80,0xbd35bd35,0xbd800000,0xbd353d35,0x3cc43d6d,0x3d6d3cc4,0x3d6dbcc4,0x3cc4bd6d,
0xbd6dbcc4,0x3cc43d6d,0x3cc4bd6d,0xbd6d3cc4,0x80003d80,0x3d35bd35,0xbd800000,0x3d353d35,0x3d6d3cc4,0xbcc4bd6d,0xbcc43d6d,0x3d6dbcc4,0x8000bd80,0xbd353d35,0x3d800000,0xbd35bd35,
0xbd6dbcc4,0x3cc43d6d,0x3cc4bd6d,0xbd6d3cc4,0x80003d80,0x3d35bd35,0xbd800000,0x3d353d35,0x3d6d3cc4,0xbcc4bd6d,0xbcc43d6d,0x3d6dbcc4,0x8000bd80,0xbd353d35,0x3d800000,0xbd35bd35,
0x3d800000,0x3cc4bd6d,0xbd35bd35,0xbd6d3cc4,0xbd553d0e,0x3c483d7b,0x3d7b3c48,0x3d0ebd55,0x8000bd80,0xbd6dbcc4,0xbd353d35,0x3cc43d6d,0x3d0e3d55,0x3d7bbc48,0x3c48bd7b,0xbd55bd0e,
0xbd800000,0xbcc43d6d,0x3d353d35,0x3d6dbcc4,0x3d55bd0e,0xbc48bd7b,0xbd7bbc48,0xbd0e3d55,0x80003d80,0x3d6d3cc4,0x3d35bd35,0xbcc4bd6d,0xbd0ebd55,0xbd7b3c48,0xbc483d7b,0x3d553d0e,
0xbc483d7b,0x3d0ebd55,0xbd553d0e,0x3d7bbc48,0x3d800000,0xbd6dbcc4,0x3d353d35,0xbcc4bd6d,0x3d7b3c48,0xbd55bd0e,0x3d0e3d55,0xbc48bd7b,0x8000bd80,0xbcc43d6d,0x3d35bd35,0xbd6d3cc4,
0x3c48bd7b,0xbd0e3d55,0x3d55bd0e,0xbd7b3c48,0xbd800000,0x3d6d3cc4,0xbd35bd35,0x3cc43d6d,0xbd7bbc48,0x3d553d0e,0xbd0ebd55,0x3c483d7b,0x80003d80,0x3cc4bd6d,0xbd353d35,0x3d6dbcc4,
0x3d800000,0x3d800000,0x3d800000,0x3d800000,0xbd800000,0xbd800000,0xbd800000,0xbd800000,0x3d800000,0x3d800000,0x3d800000,0x3d800000,0xbd800000,0xbd800000,0xbd800000,0xbd800000,
0x3d800000,0x3d800000,0x3d800000,0x3d800000,0xbd800000,0xbd800000,0xbd800000,0xbd800000,0x3d800000,0x3d800000,0x3d800000,0x3d800000,0xbd800000,0xbd800000,0xbd800000,0xbd800000,
0xbd353d35,0x3d353d35,0x3d35bd35,0xbd35bd35,0x3d800000,0xbd80,0xbd800000,0x3d80,0xbd353d35,0x3d353d35,0x3d35bd35,0xbd35bd35,0x3d800000,0xbd80,0xbd800000,0x3d80,
0xbd353d35,0x3d353d35,0x3d35bd35,0xbd35bd35,0x3d800000,0xbd80,0xbd800000,0x3d80,0xbd353d35,0x3d353d35,0x3d35bd35,0xbd35bd35,0x3d800000,0xbd80,0xbd800000,0x3d80,
0xbd80,0xbcc4bd6d,0xbd35bd35,0xbd6dbcc4,0x3c483d7b,0x3d0e3d55,0x3d553d0e,0x3d7b3c48,0x3d800000,0x3d6dbcc4,0x3d35bd35,0x3cc4bd6d,0xbd7b3c48,0xbd553d0e,0xbd0e3d55,0xbc483d7b,
0x3d80,0x3cc43d6d,0x3d353d35,0x3d6d3cc4,0xbc48bd7b,0xbd0ebd55,0xbd55bd0e,0xbd7bbc48,0xbd800000,0xbd6d3cc4,0xbd353d35,0xbcc43d6d,0x3d7bbc48,0x3d55bd0e,0x3d0ebd55,0x3c48bd7b,
0x3d553d0e,0x3c48bd7b,0xbd7b3c48,0x3d0e3d55,0xbd80,0xbd6d3cc4,0x3d353d35,0x3cc4bd6d,0xbd0e3d55,0x3d7b3c48,0xbc48bd7b,0xbd553d0e,0x3d800000,0xbcc4bd6d,0xbd353d35,0x3d6d3cc4,
0xbd55bd0e,0xbc483d7b,0x3d7bbc48,0xbd0ebd55,0x3d80,0x3d6dbcc4,0xbd35bd35,0xbcc43d6d,0x3d0ebd55,0xbd7bbc48,0x3c483d7b,0x3d55bd0e,0xbd800000,0x3cc43d6d,0x3d35bd35,0xbd6dbcc4,
0x3d800000,0x3d35bd35,0xbd80,0xbd35bd35,0xbd6d3cc4,0xbcc43d6d,0x3cc43d6d,0x3d6d3cc4,0xbd800000,0xbd353d35,0x3d80,0x3d353d35,0x3d6dbcc4,0x3cc4bd6d,0xbcc4bd6d,0xbd6dbcc4,
0x3d800000,0x3d35bd35,0xbd80,0xbd35bd35,0xbd6d3cc4,0xbcc43d6d,0x3cc43d6d,0x3d6d3cc4,0xbd800000,0xbd353d35,0x3d80,0x3d353d35,0x3d6dbcc4,0x3cc4bd6d,0xbcc4bd6d,0xbd6dbcc4,
0xbcc43d6d,0x3d6dbcc4,0xbd6dbcc4,0x3cc43d6d,0x3d800000,0xbd35bd35,0x3d80,0x3d35bd35,0x3cc4bd6d,0xbd6d3cc4,0x3d6d3cc4,0xbcc4bd6d,0xbd800000,0x3d353d35,0xbd80,0xbd353d35,
0xbcc43d6d,0x3d6dbcc4,0xbd6dbcc4,0x3cc43d6d,0x3d800000,0xbd35bd35,0x3d80,0x3d35bd35,0x3cc4bd6d,0xbd6d3cc4,0x3d6d3cc4,0xbcc4bd6d,0xbd800000,0x3d353d35,0xbd80,0xbd353d35,
0xbd80,0xbd6dbcc4,0xbd353d35,0x3cc43d6d,0x3d0e3d55,0x3d7bbc48,0x3c48bd7b,0xbd55bd0e,0xbd800000,0xbcc43d6d,0x3d353d35,0x3d6dbcc4,0x3d55bd0e,0xbc48bd7b,0xbd7bbc48,0xbd0e3d55,
0x3d80,0x3d6d3cc4,0x3d35bd35,0xbcc4bd6d,0xbd0ebd55,0xbd7b3c48,0xbc483d7b,0x3d553d0e,0x3d800000,0x3cc4bd6d,0xbd35bd35,0xbd6d3cc4,0xbd553d0e,0x3c483d7b,0x3d7b3c48,0x3d0ebd55,
0x3d7b3c48,0xbd55bd0e,0x3d0e3d55,0xbc48bd7b,0xbd80,0xbcc43d6d,0x3d35bd35,0xbd6d3cc4,0x3c48bd7b,0xbd0e3d55,0x3d55bd0e,0xbd7b3c48,0xbd800000,0x3d6d3cc4,0xbd35bd35,0x3cc43d6d,
0xbd7bbc48,0x3d553d0e,0xbd0ebd55,0x3c483d7b,0x3d80,0x3cc4bd6d,0xbd353d35,0x3d6dbcc4,0xbc483d7b,0x3d0ebd55,0xbd553d0e,0x3d7bbc48,0x3d800000,0xbd6dbcc4,0x3d353d35,0xbcc4bd6d,
0x80003d80,0x8000bd80,0x80003d80,0x8000bd80,0xbd800000,0x3d800000,0xbd800000,0x3d800000,0x80003d80,0x8000bd80,0x80003d80,0x8000bd80,0xbd800000,0x3d800000,0xbd800000,0x3d800000,
0x80003d80,0x8000bd80,0x80003d80,0x8000bd80,0xbd800000,0x3d800000,0xbd800000,0x3d800000,0x80003d80,0x8000bd80,0x80003d80,0x8000bd80,0xbd800000,0x3d800000,0xbd800000,0x3d800000,
0xbd353d35,0xbd35bd35,0x3d35bd35,0x3d353d35,0x80003d80,0xbd800000,0x8000bd80,0x3d800000,0xbd353d35,0xbd35bd35,0x3d35bd35,0x3d353d35,0x80003d80,0xbd800000,0x8000bd80,0x3d800000,
0xbd353d35,0xbd35bd35,0x3d35bd35,0x3d353d35,0x80003d80,0xbd800000,0x8000bd80,0x3d800000,0xbd353d35,0xbd35bd35,0x3d35bd35,0x3d353d35,0x80003d80,0xbd800000,0x8000bd80,0x3d800000,
0x3d800000,0xbd6d3cc4,0x3d35bd35,0xbcc43d6d,0x3c483d7b,0xbd0ebd55,0x3d553d0e,0xbd7bbc48,0x80003d80,0xbcc4bd6d,0x3d353d35,0xbd6dbcc4,0xbd7b3c48,0x3d55bd0e,0xbd0e3d55,0x3c48bd7b,
0xbd800000,0x3d6dbcc4,0xbd353d35,0x3cc4bd6d,0xbc48bd7b,0x3d0e3d55,0xbd55bd0e,0x3d7b3c48,0x8000bd80,0x3cc43d6d,0xbd35bd35,0x3d6d3cc4,0x3d7bbc48,0xbd553d0e,0x3d0ebd55,0xbc483d7b,
0x3d553d0e,0xbc483d7b,0xbd7b3c48,0xbd0ebd55,0x3d800000,0x3cc43d6d,0xbd353d35,0xbd6dbcc4,0xbd0e3d55,0xbd7bbc48,0xbc48bd7b,0x3d55bd0e,0x80003d80,0xbd6d3cc4,0xbd35bd35,0x3cc4bd6d,
0xbd55bd0e,0x3c48bd7b,0x3d7bbc48,0x3d0e3d55,0xbd800000,0xbcc4bd6d,0x3d35bd35,0x3d6d3cc4,0x3d0ebd55,0x3d7b3c48,0x3c483d7b,0xbd553d0e,0x8000bd80,0x3d6dbcc4,0x3d353d35,0xbcc43d6d,
0x80003d80,0xbd35bd35,0x3d800000,0xbd353d35,0xbd6d3cc4,0x3cc4bd6d,0x3cc43d6d,0xbd6dbcc4,0x8000bd80,0x3d353d35,0xbd800000,0x3d35bd35,0x3d6dbcc4,0xbcc43d6d,0xbcc4bd6d,0x3d6d3cc4,
0x80003d80,0xbd35bd35,0x3d800000,0xbd353d35,0xbd6d3cc4,0x3cc4bd6d,0x3cc43d6d,0xbd6dbcc4,0x8000bd80,0x3d353d35,0xbd800000,0x3d35bd35,0x3d6dbcc4,0xbcc43d6d,0xbcc4bd6d,0x3d6d3cc4,
0xbcc43d6d,0xbd6d3cc4,0xbd6dbcc4,0xbcc4bd6d,0x80003d80,0xbd353d35,0xbd800000,0xbd35bd35,0x3cc4bd6d,0x3d6dbcc4,0x3d6d3cc4,0x3cc43d6d,0x8000bd80,0x3d35bd35,0x3d800000,0x3d353d35,
0xbcc43d6d,0xbd6d3cc4,0xbd6dbcc4,0xbcc4bd6d,0x80003d80,0xbd353d35,0xbd800000,0xbd35bd35,0x3cc4bd6d,0x3d6dbcc4,0x3d6d3cc4,0x3cc43d6d,0x8000bd80,0x3d35bd35,0x3d800000,0x3d353d35,
0x3d800000,0xbcc43d6d,0xbd35bd35,0x3d6dbcc4,0x3d0e3d55,0xbd7b3c48,0x3c48bd7b,0x3d553d0e,0x8000bd80,0x3d6d3cc4,0xbd353d35,0xbcc4bd6d,0x3d55bd0e,0x3c483d7b,0xbd7bbc48,0x3d0ebd55,
0xbd800000,0x3cc4bd6d,0x3d353d35,0xbd6d3cc4,0xbd0ebd55,0x3d7bbc48,0xbc483d7b,0xbd55bd0e,0x80003d80,0xbd6dbcc4,0x3d35bd35,0x3cc43d6d,0xbd553d0e,0xbc48bd7b,0x3d7b3c48,0xbd0e3d55,
0x3d7b3c48,0x3d553d0e,0x3d0e3d55,0x3c483d7b,0x3d800000,0x3d6d3cc4,0x3d353d35,0x3cc43d6d,0x3c48bd7b,0x3d0ebd55,0x3d55bd0e,0x3d7bbc48,0x8000bd80,0x3cc4bd6d,0x3d35bd35,0x3d6dbcc4,
0xbd7bbc48,0xbd55bd0e,0xbd0ebd55,0xbc48bd7b,0xbd800000,0xbd6dbcc4,0xbd35bd35,0xbcc4bd6d,0xbc483d7b,0xbd0e3d55,0xbd553d0e,0xbd7b3c48,0x80003d80,0xbcc43d6d,0xbd353d35,0xbd6d3cc4,
0x3d800000,0xbd800000,0x3d800000,0xbd800000,0x3d80,0xbd80,0x3d80,0xbd80,0x3d800000,0xbd800000,0x3d800000,0xbd800000,0x3d80,0xbd80,0x3d80,0xbd80,
0x3d800000,0xbd800000,0x3d800000,0xbd800000,0x3d80,0xbd80,0x3d80,0xbd80,0x3d800000,0xbd800000,0x3d800000,0xbd800000,0x3d80,0xbd80,0x3d80,0xbd80,
0x3d353d35,0xbd353d35,0xbd35bd35,0x3d35bd35,0x3d800000,0x3d80,0xbd800000,0xbd80,0x3d353d35,0xbd353d35,0xbd35bd35,0x3d35bd35,0x3d800000,0x3d80,0xbd800000,0xbd80,
0x3d353d35,0xbd353d35,0xbd35bd35,0x3d35bd35,0x3d800000,0x3d80,0xbd800000,0xbd80,0x3d353d35,0xbd353d35,0xbd35bd35,0x3d35bd35,0x3d800000,0x3d80,0xbd800000,0xbd80,
0xbd80,0x3cc43d6d,0xbd35bd35,0x3d6d3cc4,0x3d7bbc48,0xbd553d0e,0x3d0ebd55,0xbc483d7b,0x3d800000,0xbd6d3cc4,0x3d35bd35,0xbcc43d6d,0x3c483d7b,0xbd0ebd55,0x3d553d0e,0xbd7bbc48,
0x3d80,0xbcc4bd6d,0x3d353d35,0xbd6dbcc4,0xbd7b3c48,0x3d55bd0e,0xbd0e3d55,0x3c48bd7b,0xbd800000,0x3d6dbcc4,0xbd353d35,0x3cc4bd6d,0xbc48bd7b,0x3d0e3d55,0xbd55bd0e,0x3d7b3c48,
0x3d0ebd55,0x3d7b3c48,0x3c483d7b,0xbd553d0e,0xbd80,0x3d6dbcc4,0x3d353d35,0xbcc43d6d,0x3d553d0e,0xbc483d7b,0xbd7b3c48,0xbd0ebd55,0x3d800000,0x3cc43d6d,0xbd353d35,0xbd6dbcc4,
0xbd0e3d55,0xbd7bbc48,0xbc48bd7b,0x3d55bd0e,0x3d80,0xbd6d3cc4,0xbd35bd35,0x3cc4bd6d,0xbd55bd0e,0x3c48bd7b,0x3d7bbc48,0x3d0e3d55,0xbd800000,0xbcc4bd6d,0x3d35bd35,0x3d6d3cc4,
0x3d800000,0xbd353d35,0xbd80,0x3d353d35,0x3cc43d6d,0xbd6dbcc4,0x3d6dbcc4,0xbcc43d6d,0xbd800000,0x3d35bd35,0x3d80,0xbd35bd35,0xbcc4bd6d,0x3d6d3cc4,0xbd6d3cc4,0x3cc4bd6d,
0x3d800000,0xbd353d35,0xbd80,0x3d353d35,0x3cc43d6d,0xbd6dbcc4,0x3d6dbcc4,0xbcc43d6d,0xbd800000,0x3d35bd35,0x3d80,0xbd35bd35,0xbcc4bd6d,0x3d6d3cc4,0xbd6d3cc4,0x3cc4bd6d,
0x3d6d3cc4,0x3cc43d6d,0xbcc43d6d,0xbd6d3cc4,0x3d800000,0x3d353d35,0x3d80,0xbd353d35,0xbd6dbcc4,0xbcc4bd6d,0x3cc4bd6d,0x3d6dbcc4,0xbd800000,0xbd35bd35,0xbd80,0x3d35bd35,
0x3d6d3cc4,0x3cc43d6d,0xbcc43d6d,0xbd6d3cc4,0x3d800000,0x3d353d35,0x3d80,0xbd353d35,0xbd6dbcc4,0xbcc4bd6d,0x3cc4bd6d,0x3d6dbcc4,0xbd800000,0xbd35bd35,0xbd80,0x3d35bd35,
0xbd80,0x3d6d3cc4,0xbd353d35,0xbcc4bd6d,0x3d55bd0e,0x3c483d7b,0xbd7bbc48,0x3d0ebd55,0xbd800000,0x3cc4bd6d,0x3d353d35,0xbd6d3cc4,0xbd0ebd55,0x3d7bbc48,0xbc483d7b,0xbd55bd0e,
0x3d80,0xbd6dbcc4,0x3d35bd35,0x3cc43d6d,0xbd553d0e,0xbc48bd7b,0x3d7b3c48,0xbd0e3d55,0x3d800000,0xbcc43d6d,0xbd35bd35,0x3d6dbcc4,0x3d0e3d55,0xbd7b3c48,0x3c48bd7b,0x3d553d0e,
0x3c48bd7b,0x3d0ebd55,0x3d55bd0e,0x3d7bbc48,0xbd80,0x3cc4bd6d,0x3d35bd35,0x3d6dbcc4,0xbd7bbc48,0xbd55bd0e,0xbd0ebd55,0xbc48bd7b,0xbd800000,0xbd6dbcc4,0xbd35bd35,0xbcc4bd6d,
0xbc483d7b,0xbd0e3d55,0xbd553d0e,0xbd7b3c48,0x3d80,0xbcc43d6d,0xbd353d35,0xbd6d3cc4,0x3d7b3c48,0x3d553d0e,0x3d0e3d55,0x3c483d7b,0x3d800000,0x3d6d3cc4,0x3d353d35,0x3cc43d6d,
0x3d80,0x3d80,0x3d80,0x3d80,0x3d80,0x3d80,0x3d80,0x3d80,0x3d80,0x3d80,0x3d80,0x3d80,0x3d80,0x3d80,0x3d80,0x3d80,
0x3d80,0x3d80,0x3d80,0x3d80,0x3d80,0x3d80,0x3d80,0x3d80,0x3d80,0x3d80,0x3d80,0x3d80,0x3d80,0x3d80,0x3d80,0x3d80,
0xbd353d35,0xbd553d0e,0xbd6d3cc4,0xbd7b3c48,0x3d80,0xbc483d7b,0xbcc43d6d,0xbd0e3d55,0xbd35bd35,0xbd0ebd55,0xbcc4bd6d,0xbc48bd7b,0xbd800000,0xbd7bbc48,0xbd6dbcc4,0xbd55bd0e,
0x3d35bd35,0x3d55bd0e,0x3d6dbcc4,0x3d7bbc48,0xbd80,0x3c48bd7b,0x3cc4bd6d,0x3d0ebd55,0x3d353d35,0x3d0e3d55,0x3cc43d6d,0x3c483d7b,0x3d800000,0x3d7b3c48,0x3d6d3cc4,0x3d553d0e,
0xbd80,0x3cc4bd6d,0x3d35bd35,0x3d6dbcc4,0x3d800000,0x3d6d3cc4,0x3d353d35,0x3cc43d6d,0x3d80,0xbcc43d6d,0xbd353d35,0xbd6d3cc4,0xbd800000,0xbd6dbcc4,0xbd35bd35,0xbcc4bd6d,
0xbd80,0x3cc4bd6d,0x3d35bd35,0x3d6dbcc4,0x3d800000,0x3d6d3cc4,0x3d353d35,0x3cc43d6d,0x3d80,0xbcc43d6d,0xbd353d35,0xbd6d3cc4,0xbd800000,0xbd6dbcc4,0xbd35bd35,0xbcc4bd6d,
0xbd353d35,0xbd7b3c48,0xbd6dbcc4,0xbd0ebd55,0x3d800000,0x3d553d0e,0x3cc43d6d,0xbc483d7b,0xbd35bd35,0xbc48bd7b,0x3cc4bd6d,0x3d55bd0e,0x3d80,0xbd0e3d55,0xbd6d3cc4,0xbd7bbc48,
0x3d35bd35,0x3d7bbc48,0x3d6d3cc4,0x3d0e3d55,0xbd800000,0xbd55bd0e,0xbcc4bd6d,0x3c48bd7b,0x3d353d35,0x3c483d7b,0xbcc43d6d,0xbd553d0e,0xbd80,0x3d0ebd55,0x3d6dbcc4,0x3d7b3c48,
0x3d80,0xbd353d35,0xbd800000,0xbd35bd35,0xbd80,0x3d35bd35,0x3d800000,0x3d353d35,0x3d80,0xbd353d35,0xbd800000,0xbd35bd35,0xbd80,0x3d35bd35,0x3d800000,0x3d353d35,
0x3d80,0xbd353d35,0xbd800000,0xbd35bd35,0xbd80,0x3d35bd35,0x3d800000,0x3d353d35,0x3d80,0xbd353d35,0xbd800000,0xbd35bd35,0xbd80,0x3d35bd35,0x3d800000,0x3d353d35,
0xbd353d35,0xbd7bbc48,0xbcc4bd6d,0x3d0ebd55,0xbd80,0x3d55bd0e,0x3d6d3cc4,0x3c483d7b,0xbd35bd35,0x3c48bd7b,0x3d6dbcc4,0x3d553d0e,0x3d800000,0x3d0e3d55,0xbcc43d6d,0xbd7b3c48,
0x3d35bd35,0x3d7b3c48,0x3cc43d6d,0xbd0e3d55,0x3d80,0xbd553d0e,0xbd6dbcc4,0xbc48bd7b,0x3d353d35,0xbc483d7b,0xbd6d3cc4,0xbd55bd0e,0xbd800000,0xbd0ebd55,0x3cc4bd6d,0x3d7bbc48,
0xbd80,0x3d6dbcc4,0x3d353d35,0xbcc43d6d,0xbd800000,0xbcc4bd6d,0x3d35bd35,0x3d6d3cc4,0x3d80,0xbd6d3cc4,0xbd35bd35,0x3cc4bd6d,0x3d800000,0x3cc43d6d,0xbd353d35,0xbd6dbcc4,
0xbd80,0x3d6dbcc4,0x3d353d35,0xbcc43d6d,0xbd800000,0xbcc4bd6d,0x3d35bd35,0x3d6d3cc4,0x3d80,0xbd6d3cc4,0xbd35bd35,0x3cc4bd6d,0x3d800000,0x3cc43d6d,0xbd353d35,0xbd6dbcc4,
0xbd353d35,0xbd55bd0e,0x3cc4bd6d,0x3d7b3c48,0xbd800000,0xbc48bd7b,0x3d6dbcc4,0x3d0e3d55,0xbd35bd35,0x3d0ebd55,0x3d6d3cc4,0xbc483d7b,0xbd80,0x3d7bbc48,0x3cc43d6d,0xbd553d0e,
0x3d35bd35,0x3d553d0e,0xbcc43d6d,0xbd7bbc48,0x3d800000,0x3c483d7b,0xbd6d3cc4,0xbd0ebd55,0x3d353d35,0xbd0e3d55,0xbd6dbcc4,0x3c48bd7b,0x3d80,0xbd7b3c48,0xbcc4bd6d,0x3d55bd0e,
0xbd800000,0xbd800000,0xbd800000,0xbd800000,0xbd800000,0xbd800000,0xbd800000,0xbd800000,0xbd800000,0xbd800000,0xbd800000,0xbd800000,0xbd800000,0xbd800000,0xbd800000,0xbd800000,
0xbd800000,0xbd800000,0xbd800000,0xbd800000,0xbd800000,0xbd800000,0xbd800000,0xbd800000,0xbd800000,0xbd800000,0xbd800000,0xbd800000,0xbd800000,0xbd800000,0xbd800000,0xbd800000,
0xbd35bd35,0xbd0ebd55,0xbcc4bd6d,0xbc48bd7b,0xbd800000,0xbd7bbc48,0xbd6dbcc4,0xbd55bd0e,0x3d35bd35,0x3d55bd0e,0x3d6dbcc4,0x3d7bbc48,0x8000bd80,0x3c48bd7b,0x3cc4bd6d,0x3d0ebd55,
0x3d353d35,0x3d0e3d55,0x3cc43d6d,0x3c483d7b,0x3d800000,0x3d7b3c48,0x3d6d3cc4,0x3d553d0e,0xbd353d35,0xbd553d0e,0xbd6d3cc4,0xbd7b3c48,0x80003d80,0xbc483d7b,0xbcc43d6d,0xbd0e3d55,
0x3d800000,0x3d6d3cc4,0x3d353d35,0x3cc43d6d,0x80003d80,0xbcc43d6d,0xbd353d35,0xbd6d3cc4,0xbd800000,0xbd6dbcc4,0xbd35bd35,0xbcc4bd6d,0x8000bd80,0x3cc4bd6d,0x3d35bd35,0x3d6dbcc4,
0x3d800000,0x3d6d3cc4,0x3d353d35,0x3cc43d6d,0x80003d80,0xbcc43d6d,0xbd353d35,0xbd6d3cc4,0xbd800000,0xbd6dbcc4,0xbd35bd35,0xbcc4bd6d,0x8000bd80,0x3cc4bd6d,0x3d35bd35,0x3d6dbcc4,
0xbd35bd35,0xbc48bd7b,0x3cc4bd6d,0x3d55bd0e,0x80003d80,0xbd0e3d55,0xbd6d3cc4,0xbd7bbc48,0x3d35bd35,0x3d7bbc48,0x3d6d3cc4,0x3d0e3d55,0xbd800000,0xbd55bd0e,0xbcc4bd6d,0x3c48bd7b,
0x3d353d35,0x3c483d7b,0xbcc43d6d,0xbd553d0e,0x8000bd80,0x3d0ebd55,0x3d6dbcc4,0x3d7b3c48,0xbd353d35,0xbd7b3c48,0xbd6dbcc4,0xbd0ebd55,0x3d800000,0x3d553d0e,0x3cc43d6d,0xbc483d7b,
0xbd800000,0xbd35bd35,0x8000bd80,0x3d35bd35,0x3d800000,0x3d353d35,0x80003d80,0xbd353d35,0xbd800000,0xbd35bd35,0x8000bd80,0x3d35bd35,0x3d800000,0x3d353d35,0x80003d80,0xbd353d35,
0xbd800000,0xbd35bd35,0x8000bd80,0x3d35bd35,0x3d800000,0x3d353d35,0x80003d80,0xbd353d35,0xbd800000,0xbd35bd35,0x8000bd80,0x3d35bd35,0x3d800000,0x3d353d35,0x80003d80,0xbd353d35,
0xbd35bd35,0x3c48bd7b,0x3d6dbcc4,0x3d553d0e,0x3d800000,0x3d0e3d55,0xbcc43d6d,0xbd7b3c48,0x3d35bd35,0x3d7b3c48,0x3cc43d6d,0xbd0e3d55,0x80003d80,0xbd553d0e,0xbd6dbcc4,0xbc48bd7b,
0x3d353d35,0xbc483d7b,0xbd6d3cc4,0xbd55bd0e,0xbd800000,0xbd0ebd55,0x3cc4bd6d,0x3d7bbc48,0xbd353d35,0xbd7bbc48,0xbcc4bd6d,0x3d0ebd55,0x8000bd80,0x3d55bd0e,0x3d6d3cc4,0x3c483d7b,
0x3d800000,0x3cc43d6d,0xbd353d35,0xbd6dbcc4,0x8000bd80,0x3d6dbcc4,0x3d353d35,0xbcc43d6d,0xbd800000,0xbcc4bd6d,0x3d35bd35,0x3d6d3cc4,0x80003d80,0xbd6d3cc4,0xbd35bd35,0x3cc4bd6d,
0x3d800000,0x3cc43d6d,0xbd353d35,0xbd6dbcc4,0x8000bd80,0x3d6dbcc4,0x3d353d35,0xbcc43d6d,0xbd800000,0xbcc4bd6d,0x3d35bd35,0x3d6d3cc4,0x80003d80,0xbd6d3cc4,0xbd35bd35,0x3cc4bd6d,
0xbd35bd35,0x3d0ebd55,0x3d6d3cc4,0xbc483d7b,0x8000bd80,0x3d7bbc48,0x3cc43d6d,0xbd553d0e,0x3d35bd35,0x3d553d0e,0xbcc43d6d,0xbd7bbc48,0x3d800000,0x3c483d7b,0xbd6d3cc4,0xbd0ebd55,
0x3d353d35,0xbd0e3d55,0xbd6dbcc4,0x3c48bd7b,0x80003d80,0xbd7b3c48,0xbcc4bd6d,0x3d55bd0e,0xbd353d35,0xbd55bd0e,0x3cc4bd6d,0x3d7b3c48,0xbd800000,0xbc48bd7b,0x3d6dbcc4,0x3d0e3d55,
0x3d80,0xbd800000,0xbd80,0x3d800000,0x3d80,0xbd800000,0xbd80,0x3d800000,0x3d80,0xbd800000,0xbd80,0x3d800000,0x3d80,0xbd800000,0xbd80,0x3d800000,
0x3d80,0xbd800000,0xbd80,0x3d800000,0x3d80,0xbd800000,0xbd80,0x3d800000,0x3d80,0xbd800000,0xbd80,0x3d800000,0x3d80,0xbd800000,0xbd80,0x3d800000,
0xbd353d35,0xbd0ebd55,0x3d6dbcc4,0x3c483d7b,0x3d80,0xbd7bbc48,0x3cc4bd6d,0x3d553d0e,0xbd35bd35,0x3d55bd0e,0x3cc43d6d,0xbd7b3c48,0xbd800000,0x3c48bd7b,0x3d6d3cc4,0xbd0e3d55,
0x3d35bd35,0x3d0e3d55,0xbd6d3cc4,0xbc48bd7b,0xbd80,0x3d7b3c48,0xbcc43d6d,0xbd55bd0e,0x3d353d35,0xbd553d0e,0xbcc4bd6d,0x3d7bbc48,0x3d800000,0xbc483d7b,0xbd6dbcc4,0x3d0ebd55,
0xbd80,0x3d6d3cc4,0xbd353d35,0xbcc4bd6d,0x3d800000,0xbcc43d6d,0xbd35bd35,0x3d6dbcc4,0x3d80,0xbd6dbcc4,0x3d35bd35,0x3cc43d6d,0xbd800000,0x3cc4bd6d,0x3d353d35,0xbd6d3cc4,
0xbd80,0x3d6d3cc4,0xbd353d35,0xbcc4bd6d,0x3d800000,0xbcc43d6d,0xbd35bd35,0x3d6dbcc4,0x3d80,0xbd6dbcc4,0x3d35bd35,0x3cc43d6d,0xbd800000,0x3cc4bd6d,0x3d353d35,0xbd6d3cc4,
0xbd353d35,0xbc48bd7b,0x3d6d3cc4,0xbd553d0e,0x3d800000,0xbd0e3d55,0xbcc4bd6d,0x3d7b3c48,0xbd35bd35,0x3d7bbc48,0xbcc43d6d,0xbd0ebd55,0x3d80,0xbd55bd0e,0x3d6dbcc4,0xbc483d7b,
0x3d35bd35,0x3c483d7b,0xbd6dbcc4,0x3d55bd0e,0xbd800000,0x3d0ebd55,0x3cc43d6d,0xbd7bbc48,0x3d353d35,0xbd7b3c48,0x3cc4bd6d,0x3d0e3d55,0xbd80,0x3d553d0e,0xbd6d3cc4,0x3c48bd7b,
0x3d80,0xbd35bd35,0x3d800000,0xbd353d35,0xbd80,0x3d353d35,0xbd800000,0x3d35bd35,0x3d80,0xbd35bd35,0x3d800000,0xbd353d35,0xbd80,0x3d353d35,0xbd800000,0x3d35bd35,
0x3d80,0xbd35bd35,0x3d800000,0xbd353d35,0xbd80,0x3d353d35,0xbd800000,0x3d35bd35,0x3d80,0xbd35bd35,0x3d800000,0xbd353d35,0xbd80,0x3d353d35,0xbd800000,0x3d35bd35,
0xbd353d35,0x3c48bd7b,0x3cc43d6d,0xbd55bd0e,0xbd80,0x3d0e3d55,0xbd6dbcc4,0x3d7bbc48,0xbd35bd35,0x3d7b3c48,0xbd6d3cc4,0x3d0ebd55,0x3d800000,0xbd553d0e,0x3cc4bd6d,0x3c483d7b,
0x3d35bd35,0xbc483d7b,0xbcc4bd6d,0x3d553d0e,0x3d80,0xbd0ebd55,0x3d6d3cc4,0xbd7b3c48,0x3d353d35,0xbd7bbc48,0x3d6dbcc4,0xbd0e3d55,0xbd800000,0x3d55bd0e,0xbcc43d6d,0xbc48bd7b,
0xbd80,0x3cc43d6d,0xbd35bd35,0x3d6d3cc4,0xbd800000,0x3d6dbcc4,0xbd353d35,0x3cc4bd6d,0x3d80,0xbcc4bd6d,0x3d353d35,0xbd6dbcc4,0x3d800000,0xbd6d3cc4,0x3d35bd35,0xbcc43d6d,
0xbd80,0x3cc43d6d,0xbd35bd35,0x3d6d3cc4,0xbd800000,0x3d6dbcc4,0xbd353d35,0x3cc4bd6d,0x3d80,0xbcc4bd6d,0x3d353d35,0xbd6dbcc4,0x3d800000,0xbd6d3cc4,0x3d35bd35,0xbcc43d6d,
0xbd353d35,0x3d0ebd55,0xbcc43d6d,0x3c48bd7b,0xbd800000,0x3d7bbc48,0xbd6d3cc4,0x3d55bd0e,0xbd35bd35,0x3d553d0e,0xbd6dbcc4,0x3d7b3c48,0xbd80,0x3c483d7b,0xbcc4bd6d,0x3d0e3d55,
0x3d35bd35,0xbd0e3d55,0x3cc4bd6d,0xbc483d7b,0x3d800000,0xbd7b3c48,0x3d6dbcc4,0xbd553d0e,0x3d353d35,0xbd55bd0e,0x3d6d3cc4,0xbd7bbc48,0x3d80,0xbc48bd7b,0x3cc43d6d,0xbd0ebd55,
0xbd800000,0x8000bd80,0x3d800000,0x80003d80,0xbd800000,0x8000bd80,0x3d800000,0x80003d80,0xbd800000,0x8000bd80,0x3d800000,0x80003d80,0xbd800000,0x8000bd80,0x3d800000,0x80003d80,
0xbd800000,0x8000bd80,0x3d800000,0x80003d80,0xbd800000,0x8000bd80,0x3d800000,0x80003d80,0xbd800000,0x8000bd80,0x3d800000,0x80003d80,0xbd800000,0x8000bd80,0x3d800000,0x80003d80,
0xbd35bd35,0x3d55bd0e,0x3cc43d6d,0xbd7b3c48,0xbd800000,0x3c48bd7b,0x3d6d3cc4,0xbd0e3d55,0x3d35bd35,0x3d0e3d55,0xbd6d3cc4,0xbc48bd7b,0x8000bd80,0x3d7b3c48,0xbcc43d6d,0xbd55bd0e,
0x3d353d35,0xbd553d0e,0xbcc4bd6d,0x3d7bbc48,0x3d800000,0xbc483d7b,0xbd6dbcc4,0x3d0ebd55,0xbd353d35,0xbd0ebd55,0x3d6dbcc4,0x3c483d7b,0x80003d80,0xbd7bbc48,0x3cc4bd6d,0x3d553d0e,
0x3d800000,0xbcc43d6d,0xbd35bd35,0x3d6dbcc4,0x80003d80,0xbd6dbcc4,0x3d35bd35,0x3cc43d6d,0xbd800000,0x3cc4bd6d,0x3d353d35,0xbd6d3cc4,0x8000bd80,0x3d6d3cc4,0xbd353d35,0xbcc4bd6d,
0x3d800000,0xbcc43d6d,0xbd35bd35,0x3d6dbcc4,0x80003d80,0xbd6dbcc4,0x3d35bd35,0x3cc43d6d,0xbd800000,0x3cc4bd6d,0x3d353d35,0xbd6d3cc4,0x8000bd80,0x3d6d3cc4,0xbd353d35,0xbcc4bd6d,
0xbd35bd35,0x3d7bbc48,0xbcc43d6d,0xbd0ebd55,0x80003d80,0xbd55bd0e,0x3d6dbcc4,0xbc483d7b,0x3d35bd35,0x3c483d7b,0xbd6dbcc4,0x3d55bd0e,0xbd800000,0x3d0ebd55,0x3cc43d6d,0xbd7bbc48,
0x3d353d35,0xbd7b3c48,0x3cc4bd6d,0x3d0e3d55,0x8000bd80,0x3d553d0e,0xbd6d3cc4,0x3c48bd7b,0xbd353d35,0xbc48bd7b,0x3d6d3cc4,0xbd553d0e,0x3d800000,0xbd0e3d55,0xbcc4bd6d,0x3d7b3c48,
0xbd800000,0x3d35bd35,0x80003d80,0xbd35bd35,0x3d800000,0xbd353d35,0x8000bd80,0x3d353d35,0xbd800000,0x3d35bd35,0x80003d80,0xbd35bd35,0x3d800000,0xbd353d35,0x8000bd80,0x3d353d35,
0xbd800000,0x3d35bd35,0x80003d80,0xbd35bd35,0x3d800000,0xbd353d35,0x8000bd80,0x3d353d35,0xbd800000,0x3d35bd35,0x80003d80,0xbd35bd35,0x3d800000,0xbd353d35,0x8000bd80,0x3d353d35,
0xbd35bd35,0x3d7b3c48,0xbd6d3cc4,0x3d0ebd55,0x3d800000,0xbd553d0e,0x3cc4bd6d,0x3c483d7b,0x3d35bd35,0xbc483d7b,0xbcc4bd6d,0x3d553d0e,0x80003d80,0xbd0ebd55,0x3d6d3cc4,0xbd7b3c48,
0x3d353d35,0xbd7bbc48,0x3d6dbcc4,0xbd0e3d55,0xbd800000,0x3d55bd0e,0xbcc43d6d,0xbc48bd7b,0xbd353d35,0x3c48bd7b,0x3cc43d6d,0xbd55bd0e,0x8000bd80,0x3d0e3d55,0xbd6dbcc4,0x3d7bbc48,
0x3d800000,0xbd6d3cc4,0x3d35bd35,0xbcc43d6d,0x8000bd80,0x3cc43d6d,0xbd35bd35,0x3d6d3cc4,0xbd800000,0x3d6dbcc4,0xbd353d35,0x3cc4bd6d,0x80003d80,0xbcc4bd6d,0x3d353d35,0xbd6dbcc4,
0x3d800000,0xbd6d3cc4,0x3d35bd35,0xbcc43d6d,0x8000bd80,0x3cc43d6d,0xbd35bd35,0x3d6d3cc4,0xbd800000,0x3d6dbcc4,0xbd353d35,0x3cc4bd6d,0x80003d80,0xbcc4bd6d,0x3d353d35,0xbd6dbcc4,
0xbd35bd35,0x3d553d0e,0xbd6dbcc4,0x3d7b3c48,0x8000bd80,0x3c483d7b,0xbcc4bd6d,0x3d0e3d55,0x3d35bd35,0xbd0e3d55,0x3cc4bd6d,0xbc483d7b,0x3d800000,0xbd7b3c48,0x3d6dbcc4,0xbd553d0e,
0x3d353d35,0xbd55bd0e,0x3d6d3cc4,0xbd7bbc48,0x80003d80,0xbc48bd7b,0x3cc43d6d,0xbd0ebd55,0xbd353d35,0x3d0ebd55,0xbcc43d6d,0x3c48bd7b,0xbd800000,0x3d7bbc48,0xbd6d3cc4,0x3d55bd0e,
0x3d80,0xbd80,0x3d80,0xbd80,0x3d80,0xbd80,0x3d80,0xbd80,0x3d80,0xbd80,0x3d80,0xbd80,0x3d80,0xbd80,0x3d80,0xbd80,
0x3d80,0xbd80,0x3d80,0xbd80,0x3d80,0xbd80,0x3d80,0xbd80,0x3d80,0xbd80,0x3d80,0xbd80,0x3d80,0xbd80,0x3d80,0xbd80,
0xbd353d35,0x3d55bd0e,0xbd6d3cc4,0x3d7bbc48,0x3d80,0x3c48bd7b,0xbcc43d6d,0x3d0ebd55,0xbd35bd35,0x3d0e3d55,0xbcc4bd6d,0x3c483d7b,0xbd800000,0x3d7b3c48,0xbd6dbcc4,0x3d553d0e,
0x3d35bd35,0xbd553d0e,0x3d6dbcc4,0xbd7b3c48,0xbd80,0xbc483d7b,0x3cc4bd6d,0xbd0e3d55,0x3d353d35,0xbd0ebd55,0x3cc43d6d,0xbc48bd7b,0x3d800000,0xbd7bbc48,0x3d6d3cc4,0xbd55bd0e,
0xbd80,0xbcc43d6d,0x3d35bd35,0xbd6d3cc4,0x3d800000,0xbd6dbcc4,0x3d353d35,0xbcc4bd6d,0x3d80,0x3cc4bd6d,0xbd353d35,0x3d6dbcc4,0xbd800000,0x3d6d3cc4,0xbd35bd35,0x3cc43d6d,
0xbd80,0xbcc43d6d,0x3d35bd35,0xbd6d3cc4,0x3d800000,0xbd6dbcc4,0x3d353d35,0xbcc4bd6d,0x3d80,0x3cc4bd6d,0xbd353d35,0x3d6dbcc4,0xbd800000,0x3d6d3cc4,0xbd35bd35,0x3cc43d6d,
0xbd353d35,0x3d7bbc48,0xbd6dbcc4,0x3d0e3d55,0x3d800000,0xbd55bd0e,0x3cc43d6d,0x3c48bd7b,0xbd35bd35,0x3c483d7b,0x3cc4bd6d,0xbd553d0e,0x3d80,0x3d0ebd55,0xbd6d3cc4,0x3d7b3c48,
0x3d35bd35,0xbd7b3c48,0x3d6d3cc4,0xbd0ebd55,0xbd800000,0x3d553d0e,0xbcc4bd6d,0xbc483d7b,0x3d353d35,0xbc48bd7b,0xbcc43d6d,0x3d55bd0e,0xbd80,0xbd0e3d55,0x3d6dbcc4,0xbd7bbc48,
0x3d80,0x3d35bd35,0xbd800000,0x3d353d35,0xbd80,0xbd353d35,0x3d800000,0xbd35bd35,0x3d80,0x3d35bd35,0xbd800000,0x3d353d35,0xbd80,0xbd353d35,0x3d800000,0xbd35bd35,
0x3d80,0x3d35bd35,0xbd800000,0x3d353d35,0xbd80,0xbd353d35,0x3d800000,0xbd35bd35,0x3d80,0x3d35bd35,0xbd800000,0x3d353d35,0xbd80,0xbd353d35,0x3d800000,0xbd35bd35,
0xbd353d35,0x3d7b3c48,0xbcc4bd6d,0xbd0e3d55,0xbd80,0xbd553d0e,0x3d6d3cc4,0xbc48bd7b,0xbd35bd35,0xbc483d7b,0x3d6dbcc4,0xbd55bd0e,0x3d800000,0xbd0ebd55,0xbcc43d6d,0x3d7bbc48,
0x3d35bd35,0xbd7bbc48,0x3cc43d6d,0x3d0ebd55,0x3d80,0x3d55bd0e,0xbd6dbcc4,0x3c483d7b,0x3d353d35,0x3c48bd7b,0xbd6d3cc4,0x3d553d0e,0xbd800000,0x3d0e3d55,0x3cc4bd6d,0xbd7b3c48,
0xbd80,0xbd6d3cc4,0x3d353d35,0x3cc4bd6d,0xbd800000,0x3cc43d6d,0x3d35bd35,0xbd6dbcc4,0x3d80,0x3d6dbcc4,0xbd35bd35,0xbcc43d6d,0x3d800000,0xbcc4bd6d,0xbd353d35,0x3d6d3cc4,
0xbd80,0xbd6d3cc4,0x3d353d35,0x3cc4bd6d,0xbd800000,0x3cc43d6d,0x3d35bd35,0xbd6dbcc4,0x3d80,0x3d6dbcc4,0xbd35bd35,0xbcc43d6d,0x3d800000,0xbcc4bd6d,0xbd353d35,0x3d6d3cc4,
0xbd353d35,0x3d553d0e,0x3cc4bd6d,0xbd7bbc48,0xbd800000,0x3c483d7b,0x3d6dbcc4,0xbd0ebd55,0xbd35bd35,0xbd0e3d55,0x3d6d3cc4,0x3c48bd7b,0xbd80,0xbd7b3c48,0x3cc43d6d,0x3d55bd0e,
0x3d35bd35,0xbd55bd0e,0xbcc43d6d,0x3d7b3c48,0x3d800000,0xbc48bd7b,0xbd6d3cc4,0x3d0e3d55,0x3d353d35,0x3d0ebd55,0xbd6dbcc4,0xbc483d7b,0x3d80,0x3d7bbc48,0xbcc4bd6d,0xbd553d0e,
0xbd800000,0x3d800000,0xbd800000,0x3d800000,0xbd800000,0x3d800000,0xbd800000,0x3d800000,0xbd800000,0x3d800000,0xbd800000,0x3d800000,0xbd800000,0x3d800000,0xbd800000,0x3d800000,
0xbd800000,0x3d800000,0xbd800000,0x3d800000,0xbd800000,0x3d800000,0xbd800000,0x3d800000,0xbd800000,0x3d800000,0xbd800000,0x3d800000,0xbd800000,0x3d800000,0xbd800000,0x3d800000,
0xbd35bd35,0x3d0e3d55,0xbcc4bd6d,0x3c483d7b,0xbd800000,0x3d7b3c48,0xbd6dbcc4,0x3d553d0e,0x3d35bd35,0xbd553d0e,0x3d6dbcc4,0xbd7b3c48,0x8000bd80,0xbc483d7b,0x3cc4bd6d,0xbd0e3d55,
0x3d353d35,0xbd0ebd55,0x3cc43d6d,0xbc48bd7b,0x3d800000,0xbd7bbc48,0x3d6d3cc4,0xbd55bd0e,0xbd353d35,0x3d55bd0e,0xbd6d3cc4,0x3d7bbc48,0x80003d80,0x3c48bd7b,0xbcc43d6d,0x3d0ebd55,
0x3d800000,0xbd6dbcc4,0x3d353d35,0xbcc4bd6d,0x80003d80,0x3cc4bd6d,0xbd353d35,0x3d6dbcc4,0xbd800000,0x3d6d3cc4,0xbd35bd35,0x3cc43d6d,0x8000bd80,0xbcc43d6d,0x3d35bd35,0xbd6d3cc4,
0x3d800000,0xbd6dbcc4,0x3d353d35,0xbcc4bd6d,0x80003d80,0x3cc4bd6d,0xbd353d35,0x3d6dbcc4,0xbd800000,0x3d6d3cc4,0xbd35bd35,0x3cc43d6d,0x8000bd80,0xbcc43d6d,0x3d35bd35,0xbd6d3cc4,
0xbd35bd35,0x3c483d7b,0x3cc4bd6d,0xbd553d0e,0x80003d80,0x3d0ebd55,0xbd6d3cc4,0x3d7b3c48,0x3d35bd35,0xbd7b3c48,0x3d6d3cc4,0xbd0ebd55,0xbd800000,0x3d553d0e,0xbcc4bd6d,0xbc483d7b,
0x3d353d35,0xbc48bd7b,0xbcc43d6d,0x3d55bd0e,0x8000bd80,0xbd0e3d55,0x3d6dbcc4,0xbd7bbc48,0xbd353d35,0x3d7bbc48,0xbd6dbcc4,0x3d0e3d55,0x3d800000,0xbd55bd0e,0x3cc43d6d,0x3c48bd7b,
0xbd800000,0x3d353d35,0x8000bd80,0xbd353d35,0x3d800000,0xbd35bd35,0x80003d80,0x3d35bd35,0xbd800000,0x3d353d35,0x8000bd80,0xbd353d35,0x3d800000,0xbd35bd35,0x80003d80,0x3d35bd35,
0xbd800000,0x3d353d35,0x8000bd80,0xbd353d35,0x3d800000,0xbd35bd35,0x80003d80,0x3d35bd35,0xbd800000,0x3d353d35,0x8000bd80,0xbd353d35,0x3d800000,0xbd35bd35,0x80003d80,0x3d35bd35,
0xbd35bd35,0xbc483d7b,0x3d6dbcc4,0xbd55bd0e,0x3d800000,0xbd0ebd55,0xbcc43d6d,0x3d7bbc48,0x3d35bd35,0xbd7bbc48,0x3cc43d6d,0x3d0ebd55,0x80003d80,0x3d55bd0e,0xbd6dbcc4,0x3c483d7b,
0x3d353d35,0x3c48bd7b,0xbd6d3cc4,0x3d553d0e,0xbd800000,0x3d0e3d55,0x3cc4bd6d,0xbd7b3c48,0xbd353d35,0x3d7b3c48,0xbcc4bd6d,0xbd0e3d55,0x8000bd80,0xbd553d0e,0x3d6d3cc4,0xbc48bd7b,
0x3d800000,0xbcc4bd6d,0xbd353d35,0x3d6d3cc4,0x8000bd80,0xbd6d3cc4,0x3d353d35,0x3cc4bd6d,0xbd800000,0x3cc43d6d,0x3d35bd35,0xbd6dbcc4,0x80003d80,0x3d6dbcc4,0xbd35bd35,0xbcc43d6d,
0x3d800000,0xbcc4bd6d,0xbd353d35,0x3d6d3cc4,0x8000bd80,0xbd6d3cc4,0x3d353d35,0x3cc4bd6d,0xbd800000,0x3cc43d6d,0x3d35bd35,0xbd6dbcc4,0x80003d80,0x3d6dbcc4,0xbd35bd35,0xbcc43d6d,
0xbd35bd35,0xbd0e3d55,0x3d6d3cc4,0x3c48bd7b,0x8000bd80,0xbd7b3c48,0x3cc43d6d,0x3d55bd0e,0x3d35bd35,0xbd55bd0e,0xbcc43d6d,0x3d7b3c48,0x3d800000,0xbc48bd7b,0xbd6d3cc4,0x3d0e3d55,
0x3d353d35,0x3d0ebd55,0xbd6dbcc4,0xbc483d7b,0x80003d80,0x3d7bbc48,0xbcc4bd6d,0xbd553d0e,0xbd353d35,0x3d553d0e,0x3cc4bd6d,0xbd7bbc48,0xbd800000,0x3c483d7b,0x3d6dbcc4,0xbd0ebd55,
0x3d80,0x3d800000,0xbd80,0xbd800000,0x3d80,0x3d800000,0xbd80,0xbd800000,0x3d80,0x3d800000,0xbd80,0xbd800000,0x3d80,0x3d800000,0xbd80,0xbd800000,
0x3d80,0x3d800000,0xbd80,0xbd800000,0x3d80,0x3d800000,0xbd80,0xbd800000,0x3d80,0x3d800000,0xbd80,0xbd800000,0x3d80,0x3d800000,0xbd80,0xbd800000,
0xbd353d35,0x3d0e3d55,0x3d6dbcc4,0xbc48bd7b,0x3d80,0x3d7b3c48,0x3cc4bd6d,0xbd55bd0e,0xbd35bd35,0xbd553d0e,0x3cc43d6d,0x3d7bbc48,0xbd800000,0xbc483d7b,0x3d6d3cc4,0x3d0ebd55,
0x3d35bd35,0xbd0ebd55,0xbd6d3cc4,0x3c483d7b,0xbd80,0xbd7bbc48,0xbcc43d6d,0x3d553d0e,0x3d353d35,0x3d55bd0e,0xbcc4bd6d,0xbd7b3c48,0x3d800000,0x3c48bd7b,0xbd6dbcc4,0xbd0e3d55,
0xbd80,0xbd6dbcc4,0xbd353d35,0x3cc43d6d,0x3d800000,0x3cc4bd6d,0xbd35bd35,0xbd6d3cc4,0x3d80,0x3d6d3cc4,0x3d35bd35,0xbcc4bd6d,0xbd800000,0xbcc43d6d,0x3d353d35,0x3d6dbcc4,
0xbd80,0xbd6dbcc4,0xbd353d35,0x3cc43d6d,0x3d800000,0x3cc4bd6d,0xbd35bd35,0xbd6d3cc4,0x3d80,0x3d6d3cc4,0x3d35bd35,0xbcc4bd6d,0xbd800000,0xbcc43d6d,0x3d353d35,0x3d6dbcc4,
0xbd353d35,0x3c483d7b,0x3d6d3cc4,0x3d55bd0e,0x3d800000,0x3d0ebd55,0xbcc4bd6d,0xbd7bbc48,0xbd35bd35,0xbd7b3c48,0xbcc43d6d,0x3d0e3d55,0x3d80,0x3d553d0e,0x3d6dbcc4,0x3c48bd7b,
0x3d35bd35,0xbc48bd7b,0xbd6dbcc4,0xbd553d0e,0xbd800000,0xbd0e3d55,0x3cc43d6d,0x3d7b3c48,0x3d353d35,0x3d7bbc48,0x3cc4bd6d,0xbd0ebd55,0xbd80,0xbd55bd0e,0xbd6d3cc4,0xbc483d7b,
0x3d80,0x3d353d35,0x3d800000,0x3d35bd35,0xbd80,0xbd35bd35,0xbd800000,0xbd353d35,0x3d80,0x3d353d35,0x3d800000,0x3d35bd35,0xbd80,0xbd35bd35,0xbd800000,0xbd353d35,
0x3d80,0x3d353d35,0x3d800000,0x3d35bd35,0xbd80,0xbd35bd35,0xbd800000,0xbd353d35,0x3d80,0x3d353d35,0x3d800000,0x3d35bd35,0xbd80,0xbd35bd35,0xbd800000,0xbd353d35,
0xbd353d35,0xbc483d7b,0x3cc43d6d,0x3d553d0e,0xbd80,0xbd0ebd55,0xbd6dbcc4,0xbd7b3c48,0xbd35bd35,0xbd7bbc48,0xbd6d3cc4,0xbd0e3d55,0x3d800000,0x3d55bd0e,0x3cc4bd6d,0xbc48bd7b,
0x3d35bd35,0x3c48bd7b,0xbcc4bd6d,0xbd55bd0e,0x3d80,0x3d0e3d55,0x3d6d3cc4,0x3d7bbc48,0x3d353d35,0x3d7b3c48,0x3d6dbcc4,0x3d0ebd55,0xbd800000,0xbd553d0e,0xbcc43d6d,0x3c483d7b,
0xbd80,0xbcc4bd6d,0xbd35bd35,0xbd6dbcc4,0xbd800000,0xbd6d3cc4,0xbd353d35,0xbcc43d6d,0x3d80,0x3cc43d6d,0x3d353d35,0x3d6d3cc4,0x3d800000,0x3d6dbcc4,0x3d35bd35,0x3cc4bd6d,
0xbd80,0xbcc4bd6d,0xbd35bd35,0xbd6dbcc4,0xbd800000,0xbd6d3cc4,0xbd353d35,0xbcc43d6d,0x3d80,0x3cc43d6d,0x3d353d35,0x3d6d3cc4,0x3d800000,0x3d6dbcc4,0x3d35bd35,0x3cc4bd6d,
0xbd353d35,0xbd0e3d55,0xbcc43d6d,0xbc483d7b,0xbd800000,0xbd7b3c48,0xbd6d3cc4,0xbd553d0e,0xbd35bd35,0xbd55bd0e,0xbd6dbcc4,0xbd7bbc48,0xbd80,0xbc48bd7b,0xbcc4bd6d,0xbd0ebd55,
0x3d35bd35,0x3d0ebd55,0x3cc4bd6d,0x3c48bd7b,0x3d800000,0x3d7bbc48,0x3d6dbcc4,0x3d55bd0e,0x3d353d35,0x3d553d0e,0x3d6d3cc4,0x3d7b3c48,0x3d80,0x3c483d7b,0x3cc43d6d,0x3d0e3d55,
0xbd800000,0x80003d80,0x3d800000,0x8000bd80,0xbd800000,0x80003d80,0x3d800000,0x8000bd80,0xbd800000,0x80003d80,0x3d800000,0x8000bd80,0xbd800000,0x80003d80,0x3d800000,0x8000bd80,
0xbd800000,0x80003d80,0x3d800000,0x8000bd80,0xbd800000,0x80003d80,0x3d800000,0x8000bd80,0xbd800000,0x80003d80,0x3d800000,0x8000bd80,0xbd800000,0x80003d80,0x3d800000,0x8000bd80,
0xbd35bd35,0xbd553d0e,0x3cc43d6d,0x3d7bbc48,0xbd800000,0xbc483d7b,0x3d6d3cc4,0x3d0ebd55,0x3d35bd35,0xbd0ebd55,0xbd6d3cc4,0x3c483d7b,0x8000bd80,0xbd7bbc48,0xbcc43d6d,0x3d553d0e,
0x3d353d35,0x3d55bd0e,0xbcc4bd6d,0xbd7b3c48,0x3d800000,0x3c48bd7b,0xbd6dbcc4,0xbd0e3d55,0xbd353d35,0x3d0e3d55,0x3d6dbcc4,0xbc48bd7b,0x80003d80,0x3d7b3c48,0x3cc4bd6d,0xbd55bd0e,
0x3d800000,0x3cc4bd6d,0xbd35bd35,0xbd6d3cc4,0x80003d80,0x3d6d3cc4,0x3d35bd35,0xbcc4bd6d,0xbd800000,0xbcc43d6d,0x3d353d35,0x3d6dbcc4,0x8000bd80,0xbd6dbcc4,0xbd353d35,0x3cc43d6d,
0x3d800000,0x3cc4bd6d,0xbd35bd35,0xbd6d3cc4,0x80003d80,0x3d6d3cc4,0x3d35bd35,0xbcc4bd6d,0xbd800000,0xbcc43d6d,0x3d353d35,0x3d6dbcc4,0x8000bd80,0xbd6dbcc4,0xbd353d35,0x3cc43d6d,
0xbd35bd35,0xbd7b3c48,0xbcc43d6d,0x3d0e3d55,0x80003d80,0x3d553d0e,0x3d6dbcc4,0x3c48bd7b,0x3d35bd35,0xbc48bd7b,0xbd6dbcc4,0xbd553d0e,0xbd800000,0xbd0e3d55,0x3cc43d6d,0x3d7b3c48,
0x3d353d35,0x3d7bbc48,0x3cc4bd6d,0xbd0ebd55,0x8000bd80,0xbd55bd0e,0xbd6d3cc4,0xbc483d7b,0xbd353d35,0x3c483d7b,0x3d6d3cc4,0x3d55bd0e,0x3d800000,0x3d0ebd55,0xbcc4bd6d,0xbd7bbc48,
0xbd800000,0xbd353d35,0x80003d80,0x3d353d35,0x3d800000,0x3d35bd35,0x8000bd80,0xbd35bd35,0xbd800000,0xbd353d35,0x80003d80,0x3d353d35,0x3d800000,0x3d35bd35,0x8000bd80,0xbd35bd35,
0xbd800000,0xbd353d35,0x80003d80,0x3d353d35,0x3d800000,0x3d35bd35,0x8000bd80,0xbd35bd35,0xbd800000,0xbd353d35,0x80003d80,0x3d353d35,0x3d800000,0x3d35bd35,0x8000bd80,0xbd35bd35,
0xbd35bd35,0xbd7bbc48,0xbd6d3cc4,0xbd0e3d55,0x3d800000,0x3d55bd0e,0x3cc4bd6d,0xbc48bd7b,0x3d35bd35,0x3c48bd7b,0xbcc4bd6d,0xbd55bd0e,0x80003d80,0x3d0e3d55,0x3d6d3cc4,0x3d7bbc48,
0x3d353d35,0x3d7b3c48,0x3d6dbcc4,0x3d0ebd55,0xbd800000,0xbd553d0e,0xbcc43d6d,0x3c483d7b,0xbd353d35,0xbc483d7b,0x3cc43d6d,0x3d553d0e,0x8000bd80,0xbd0ebd55,0xbd6dbcc4,0xbd7b3c48,
0x3d800000,0x3d6dbcc4,0x3d35bd35,0x3cc4bd6d,0x8000bd80,0xbcc4bd6d,0xbd35bd35,0xbd6dbcc4,0xbd800000,0xbd6d3cc4,0xbd353d35,0xbcc43d6d,0x80003d80,0x3cc43d6d,0x3d353d35,0x3d6d3cc4,
0x3d800000,0x3d6dbcc4,0x3d35bd35,0x3cc4bd6d,0x8000bd80,0xbcc4bd6d,0xbd35bd35,0xbd6dbcc4,0xbd800000,0xbd6d3cc4,0xbd353d35,0xbcc43d6d,0x80003d80,0x3cc43d6d,0x3d353d35,0x3d6d3cc4,
0xbd35bd35,0xbd55bd0e,0xbd6dbcc4,0xbd7bbc48,0x8000bd80,0xbc48bd7b,0xbcc4bd6d,0xbd0ebd55,0x3d35bd35,0x3d0ebd55,0x3cc4bd6d,0x3c48bd7b,0x3d800000,0x3d7bbc48,0x3d6dbcc4,0x3d55bd0e,
0x3d353d35,0x3d553d0e,0x3d6d3cc4,0x3d7b3c48,0x80003d80,0x3c483d7b,0x3cc43d6d,0x3d0e3d55,0xbd353d35,0xbd0e3d55,0xbcc43d6d,0xbc483d7b,0xbd800000,0xbd7b3c48,0xbd6d3cc4,0xbd553d0e,
0x3d80,0xbb493d80,0xbbc93d7f,0xbc163d7d,0xbc483d7b,0xbc793d78,0xbc953d75,0xbcac3d71,0xbcc43d6d,0xbcdb3d67,0xbcf13d62,0xbd043d5c,0xbd0e3d55,0xbd183d4e,0xbd223d46,0xbd2c3d3e,
0xbd353d35,0xbd3e3d2c,0xbd463d22,0xbd4e3d18,0xbd553d0e,0xbd5c3d04,0xbd623cf1,0xbd673cdb,0xbd6d3cc4,0xbd713cac,0xbd753c95,0xbd783c79,0xbd7b3c48,0xbd7d3c16,0xbd7f3bc9,0xbd803b49,
0xbd553d0e,0xbd713cac,0xbd7f3bc9,0xbd7dbc16,0x3d80,0xbc793d78,0xbcf13d62,0xbd2c3d3e,0xbc48bd7b,0x3b49bd80,0x3c95bd75,0x3d04bd5c,0xbd6dbcc4,0xbd4ebd18,0xbd22bd46,0xbcdbbd67,
0x3d7b3c48,0x3d673cdb,0x3d463d22,0x3d183d4e,0x3d35bd35,0x3d5cbd04,0x3d75bc95,0x3d80bb49,0xbd0e3d55,0xbd3e3d2c,0xbd623cf1,0xbd783c79,0x3cc43d6d,0x3c163d7d,0xbbc93d7f,0xbcac3d71,
0x3cc4bd6d,0x3d3ebd2c,0x3d75bc95,0x3d7d3c16,0x3d553d0e,0x3d043d5c,0x3bc93d7f,0xbcac3d71,0x3d80,0xbcdb3d67,0xbd463d22,0xbd783c79,0xbd7bbc48,0xbd4ebd18,0xbcf1bd62,0xbb49bd80,
0x3d6dbcc4,0x3d803b49,0x3d623cf1,0x3d183d4e,0x3c483d7b,0xbc793d78,0xbd223d46,0xbd673cdb,0xbd353d35,0xbd713cac,0xbd7fbbc9,0xbd5cbd04,0xbd0ebd55,0xbc16bd7d,0x3c95bd75,0x3d2cbd3e,
0xbd7b3c48,0xbd67bcdb,0xbcf1bd62,0x3c16bd7d,0x3d6d3cc4,0x3d043d5c,0xbbc93d7f,0xbd2c3d3e,0xbd0ebd55,0x3b49bd80,0x3d22bd46,0x3d78bc79,0x3d80,0xbd183d4e,0xbd753c95,0xbd71bcac,
0x3d553d0e,0x3cac3d71,0xbc953d75,0xbd4e3d18,0xbcc4bd6d,0x3c79bd78,0x3d46bd22,0x3d80bb49,0xbc483d7b,0xbd3e3d2c,0xbd7f3bc9,0xbd5cbd04,0x3d35bd35,0x3d7dbc16,0x3d623cf1,0x3cdb3d67,
0xbd353d35,0xbd80bb49,0xbd22bd46,0x3c16bd7d,0x3d55bd0e,0x3d783c79,0x3cf13d62,0xbcac3d71,0xbd6d3cc4,0xbd67bcdb,0xbc95bd75,0x3d04bd5c,0x3d7bbc48,0x3d4e3d18,0x3bc93d7f,0xbd2c3d3e,
0x3d80,0xbd3e3d2c,0xbd7fbbc9,0xbd18bd4e,0x3c48bd7b,0x3d5cbd04,0x3d753c95,0x3cdb3d67,0xbcc43d6d,0xbd713cac,0xbd62bcf1,0xbc79bd78,0x3d0ebd55,0x3d7dbc16,0x3d463d22,0x3b493d80,
0xbd7bbc48,0xbcacbd71,0x3d22bd46,0x3d7d3c16,0x3d35bd35,0x3d783c79,0x3c953d75,0xbd2c3d3e,0x3d0ebd55,0x3d803b49,0x3cf13d62,0xbd043d5c,0x3cc43d6d,0xbd183d4e,0xbd7fbbc9,0xbcdbbd67,
0x3d55bd0e,0x3d673cdb,0x3bc93d7f,0xbd4e3d18,0x3d80,0xbd5c3d04,0xbd62bcf1,0xbb49bd80,0x3c483d7b,0xbd3e3d2c,0xbd75bc95,0xbc79bd78,0xbd6dbcc4,0xbc16bd7d,0x3d46bd22,0x3d713cac,
0x3d6dbcc4,0x3d2c3d3e,0xbcf13d62,0xbd7dbc16,0xbc48bd7b,0x3d5cbd04,0x3d463d22,0xbcac3d71,0xbd353d35,0xbd67bcdb,0x3bc9bd7f,0x3d78bc79,0x3d0e3d55,0xbd183d4e,0xbd75bc95,0xbb49bd80,
0x3cc4bd6d,0x3d803b49,0x3c953d75,0xbd4e3d18,0xbd55bd0e,0x3c79bd78,0x3d7fbbc9,0x3cdb3d67,0x3d80,0xbd713cac,0xbd22bd46,0x3d04bd5c,0x3d7b3c48,0x3c163d7d,0xbd623cf1,0xbd3ebd2c,
0xbd55bd0e,0x3cdbbd67,0x3d753c95,0xbc163d7d,0xbcc4bd6d,0x3d5cbd04,0x3d223d46,0xbd2c3d3e,0x3c48bd7b,0x3d803b49,0x3bc93d7f,0xbd783c79,0x3d35bd35,0x3d4e3d18,0xbcf13d62,0xbd71bcac,
0x3d7bbc48,0x3cac3d71,0xbd623cf1,0xbd18bd4e,0x3d6d3cc4,0xbc793d78,0xbd7fbbc9,0xbb49bd80,0x3d0e3d55,0xbd3e3d2c,0xbd46bd22,0x3d04bd5c,0x3d80,0xbd7d3c16,0xbc95bd75,0x3d67bcdb,
0xbd800000,0xbd80bb49,0xbd7fbbc9,0xbd7dbc16,0xbd7bbc48,0xbd78bc79,0xbd75bc95,0xbd71bcac,0xbd6dbcc4,0xbd67bcdb,0xbd62bcf1,0xbd5cbd04,0xbd55bd0e,0xbd4ebd18,0xbd46bd22,0xbd3ebd2c,
0xbd35bd35,0xbd2cbd3e,0xbd22bd46,0xbd18bd4e,0xbd0ebd55,0xbd04bd5c,0xbcf1bd62,0xbcdbbd67,0xbcc4bd6d,0xbcacbd71,0xbc95bd75,0xbc79bd78,0xbc48bd7b,0xbc16bd7d,0xbbc9bd7f,0xbb49bd80,
0xbd0ebd55,0xbcacbd71,0xbbc9bd7f,0x3c16bd7d,0xbd800000,0xbd78bc79,0xbd62bcf1,0xbd3ebd2c,0x3d7bbc48,0x3d803b49,0x3d753c95,0x3d5c3d04,0x3cc4bd6d,0x3d18bd4e,0x3d46bd22,0x3d67bcdb,
0xbc483d7b,0xbcdb3d67,0xbd223d46,0xbd4e3d18,0x3d353d35,0x3d043d5c,0x3c953d75,0x3b493d80,0xbd55bd0e,0xbd2cbd3e,0xbcf1bd62,0xbc79bd78,0xbd6d3cc4,0xbd7d3c16,0xbd7fbbc9,0xbd71bcac,
0x3d6d3cc4,0x3d2c3d3e,0x3c953d75,0xbc163d7d,0xbd0e3d55,0xbd5c3d04,0xbd7f3bc9,0xbd71bcac,0xbd800000,0xbd67bcdb,0xbd22bd46,0xbc79bd78,0x3c48bd7b,0x3d18bd4e,0x3d62bcf1,0x3d80bb49,
0x3cc43d6d,0xbb493d80,0xbcf13d62,0xbd4e3d18,0xbd7b3c48,0xbd78bc79,0xbd46bd22,0xbcdbbd67,0xbd35bd35,0xbcacbd71,0x3bc9bd7f,0x3d04bd5c,0x3d55bd0e,0x3d7dbc16,0x3d753c95,0x3d3e3d2c,
0xbc48bd7b,0x3cdbbd67,0x3d62bcf1,0x3d7d3c16,0xbcc43d6d,0xbd5c3d04,0xbd7fbbc9,0xbd3ebd2c,0x3d55bd0e,0x3d803b49,0x3d463d22,0x3c793d78,0xbd800000,0xbd4ebd18,0xbc95bd75,0x3cacbd71,
0xbd0e3d55,0xbd713cac,0xbd75bc95,0xbd18bd4e,0x3d6dbcc4,0x3d783c79,0x3d223d46,0x3b493d80,0xbd7bbc48,0xbd2cbd3e,0xbbc9bd7f,0x3d04bd5c,0x3d353d35,0x3c163d7d,0xbcf13d62,0xbd673cdb,
0xbd35bd35,0x3b49bd80,0x3d46bd22,0x3d7d3c16,0x3d0e3d55,0xbc793d78,0xbd623cf1,0xbd71bcac,0xbcc4bd6d,0x3cdbbd67,0x3d75bc95,0x3d5c3d04,0x3c483d7b,0xbd183d4e,0xbd7f3bc9,0xbd3ebd2c,
0xbd800000,0xbd2cbd3e,0x3bc9bd7f,0x3d4ebd18,0x3d7b3c48,0x3d043d5c,0xbc953d75,0xbd673cdb,0xbd6dbcc4,0xbcacbd71,0x3cf1bd62,0x3d78bc79,0x3d553d0e,0x3c163d7d,0xbd223d46,0xbd803b49,
0x3c48bd7b,0x3d71bcac,0x3d463d22,0xbc163d7d,0x3d353d35,0xbc793d78,0xbd753c95,0xbd3ebd2c,0x3d553d0e,0xbb493d80,0xbd623cf1,0xbd5cbd04,0xbd6d3cc4,0xbd4ebd18,0x3bc9bd7f,0x3d67bcdb,
0x3d0e3d55,0xbcdb3d67,0xbd7f3bc9,0xbd18bd4e,0xbd800000,0xbd04bd5c,0x3cf1bd62,0x3d80bb49,0xbd7b3c48,0xbd2cbd3e,0x3c95bd75,0x3d78bc79,0x3cc4bd6d,0x3d7dbc16,0x3d223d46,0xbcac3d71,
0x3cc43d6d,0xbd3e3d2c,0xbd62bcf1,0x3c16bd7d,0x3d7bbc48,0x3d043d5c,0xbd223d46,0xbd71bcac,0xbd35bd35,0x3cdbbd67,0x3d7f3bc9,0x3c793d78,0xbd553d0e,0xbd4ebd18,0x3c95bd75,0x3d80bb49,
0x3d6d3cc4,0xbb493d80,0xbd753c95,0xbd18bd4e,0x3d0ebd55,0x3d783c79,0x3bc93d7f,0xbd673cdb,0xbd800000,0xbcacbd71,0x3d46bd22,0x3d5c3d04,0xbc483d7b,0xbd7d3c16,0xbcf1bd62,0x3d2cbd3e,
0x3d0ebd55,0x3d673cdb,0xbc953d75,0xbd7dbc16,0x3d6dbcc4,0x3d043d5c,0xbd463d22,0xbd3ebd2c,0x3d7b3c48,0xbb493d80,0xbd7f3bc9,0xbc79bd78,0x3d353d35,0xbd183d4e,0xbd62bcf1,0x3cacbd71,
0x3c483d7b,0xbd713cac,0xbcf1bd62,0x3d4ebd18,0xbcc43d6d,0xbd78bc79,0x3bc9bd7f,0x3d80bb49,0xbd553d0e,0xbd2cbd3e,0x3d22bd46,0x3d5c3d04,0xbd800000,0xbc16bd7d,0x3d75bc95,0x3cdb3d67,
0x3d80,0xbd80bb49,0x3bc9bd7f,0x3d7d3c16,0xbc483d7b,0xbd78bc79,0x3c95bd75,0x3d713cac,0xbcc43d6d,0xbd67bcdb,0x3cf1bd62,0x3d5c3d04,0xbd0e3d55,0xbd4ebd18,0x3d22bd46,0x3d3e3d2c,
0xbd353d35,0xbd2cbd3e,0x3d46bd22,0x3d183d4e,0xbd553d0e,0xbd04bd5c,0x3d62bcf1,0x3cdb3d67,0xbd6d3cc4,0xbcacbd71,0x3d75bc95,0x3c793d78,0xbd7b3c48,0xbc16bd7d,0x3d7fbbc9,0x3b493d80,
0xbd553d0e,0xbcacbd71,0x3d7fbbc9,0xbc163d7d,0x3d80,0xbd78bc79,0x3cf1bd62,0x3d3e3d2c,0xbc48bd7b,0x3d803b49,0xbc953d75,0xbd5cbd04,0xbd6dbcc4,0x3d18bd4e,0x3d223d46,0xbd673cdb,
0x3d7b3c48,0xbcdb3d67,0xbd46bd22,0x3d4ebd18,0x3d35bd35,0x3d043d5c,0xbd753c95,0xbb49bd80,0xbd0e3d55,0xbd2cbd3e,0x3d62bcf1,0x3c793d78,0x3cc43d6d,0xbd7d3c16,0x3bc9bd7f,0x3d713cac,
0x3cc4bd6d,0x3d2c3d3e,0xbd753c95,0x3c16bd7d,0x3d553d0e,0xbd5c3d04,0xbbc9bd7f,0x3d713cac,0x3d80,0xbd67bcdb,0x3d46bd22,0x3c793d78,0xbd7bbc48,0x3d18bd4e,0x3cf13d62,0xbd803b49,
0x3d6dbcc4,0xbb493d80,0xbd62bcf1,0x3d4ebd18,0x3c483d7b,0xbd78bc79,0x3d22bd46,0x3cdb3d67,0xbd353d35,0xbcacbd71,0x3d7f3bc9,0xbd043d5c,0xbd0ebd55,0x3d7dbc16,0xbc953d75,0xbd3ebd2c,
0xbd7b3c48,0x3cdbbd67,0x3cf13d62,0xbd7dbc16,0x3d6d3cc4,0xbd5c3d04,0x3bc9bd7f,0x3d3e3d2c,0xbd0ebd55,0x3d803b49,0xbd223d46,0xbc79bd78,0x3d80,0xbd4ebd18,0x3d75bc95,0xbcac3d71,
0x3d553d0e,0xbd713cac,0x3c95bd75,0x3d183d4e,0xbcc4bd6d,0x3d783c79,0xbd463d22,0xbb49bd80,0xbc483d7b,0xbd2cbd3e,0x3d7fbbc9,0xbd043d5c,0x3d35bd35,0x3c163d7d,0xbd62bcf1,0x3d67bcdb,
0xbd353d35,0x3b49bd80,0x3d223d46,0xbd7dbc16,0x3d55bd0e,0xbc793d78,0xbcf1bd62,0x3d713cac,0xbd6d3cc4,0x3cdbbd67,0x3c953d75,0xbd5cbd04,0x3d7bbc48,0xbd183d4e,0xbbc9bd7f,0x3d3e3d2c,
0x3d80,0xbd2cbd3e,0x3d7f3bc9,0xbd4e3d18,0x3c48bd7b,0x3d043d5c,0xbd75bc95,0x3d67bcdb,0xbcc43d6d,0xbcacbd71,0x3d623cf1,0xbd783c79,0x3d0ebd55,0x3c163d7d,0xbd46bd22,0x3d80bb49,
0xbd7bbc48,0x3d71bcac,0xbd223d46,0x3c16bd7d,0x3d35bd35,0xbc793d78,0xbc95bd75,0x3d3e3d2c,0x3d0ebd55,0xbb493d80,0xbcf1bd62,0x3d5c3d04,0x3cc43d6d,0xbd4ebd18,0x3d7f3bc9,0xbd673cdb,
0x3d55bd0e,0xbcdb3d67,0xbbc9bd7f,0x3d183d4e,0x3d80,0xbd04bd5c,0x3d623cf1,0xbd803b49,0x3c483d7b,0xbd2cbd3e,0x3d753c95,0xbd783c79,0xbd6dbcc4,0x3d7dbc16,0xbd463d22,0x3cacbd71,
0x3d6dbcc4,0xbd3e3d2c,0x3cf1bd62,0xbc163d7d,0xbc48bd7b,0x3d043d5c,0xbd46bd22,0x3d713cac,0xbd353d35,0x3cdbbd67,0xbbc93d7f,0xbc79bd78,0x3d0e3d55,0xbd4ebd18,0x3d753c95,0xbd803b49,
0x3cc4bd6d,0xbb493d80,0xbc95bd75,0x3d183d4e,0xbd55bd0e,0x3d783c79,0xbd7f3bc9,0x3d67bcdb,0x3d80,0xbcacbd71,0x3d223d46,0xbd5cbd04,0x3d7b3c48,0xbd7d3c16,0x3d62bcf1,0xbd2c3d3e,
0xbd55bd0e,0x3d673cdb,0xbd75bc95,0x3d7d3c16,0xbcc4bd6d,0x3d043d5c,0xbd22bd46,0x3d3e3d2c,0x3c48bd7b,0xbb493d80,0xbbc9bd7f,0x3c793d78,0x3d35bd35,0xbd183d4e,0x3cf1bd62,0xbcac3d71,
0x3d7bbc48,0xbd713cac,0x3d62bcf1,0xbd4e3d18,0x3d6d3cc4,0xbd78bc79,0x3d7f3bc9,0xbd803b49,0x3d0e3d55,0xbd2cbd3e,0x3d463d22,0xbd5cbd04,0x3d80,0xbc16bd7d,0x3c953d75,0xbcdbbd67,
0xbd800000,0x3b49bd80,0x3d7f3bc9,0xbc163d7d,0xbd7bbc48,0x3c79bd78,0x3d753c95,0xbcac3d71,0xbd6dbcc4,0x3cdbbd67,0x3d623cf1,0xbd043d5c,0xbd55bd0e,0x3d18bd4e,0x3d463d22,0xbd2c3d3e,
0xbd35bd35,0x3d3ebd2c,0x3d223d46,0xbd4e3d18,0xbd0ebd55,0x3d5cbd04,0x3cf13d62,0xbd673cdb,0xbcc4bd6d,0x3d71bcac,0x3c953d75,0xbd783c79,0xbc48bd7b,0x3d7dbc16,0x3bc93d7f,0xbd803b49,
0xbd0ebd55,0x3d71bcac,0x3bc93d7f,0xbd7dbc16,0xbd800000,0x3c79bd78,0x3d623cf1,0xbd2c3d3e,0x3d7bbc48,0xbb493d80,0xbd75bc95,0x3d04bd5c,0x3cc4bd6d,0x3d4e3d18,0xbd463d22,0xbcdbbd67,
0xbc483d7b,0xbd67bcdb,0x3d22bd46,0x3d183d4e,0x3d353d35,0xbd5c3d04,0xbc95bd75,0x3d80bb49,0xbd55bd0e,0x3d3ebd2c,0x3cf13d62,0xbd783c79,0xbd6d3cc4,0xbc16bd7d,0x3d7f3bc9,0xbcac3d71,
0x3d6d3cc4,0xbd3e3d2c,0xbc95bd75,0x3d7d3c16,0xbd0e3d55,0xbd04bd5c,0x3d7fbbc9,0xbcac3d71,0xbd800000,0x3cdbbd67,0x3d223d46,0xbd783c79,0x3c48bd7b,0x3d4e3d18,0xbd623cf1,0xbb49bd80,
0x3cc43d6d,0xbd80bb49,0x3cf1bd62,0x3d183d4e,0xbd7b3c48,0x3c79bd78,0x3d463d22,0xbd673cdb,0xbd35bd35,0x3d71bcac,0xbbc93d7f,0xbd5cbd04,0x3d55bd0e,0x3c163d7d,0xbd75bc95,0x3d2cbd3e,
0xbc48bd7b,0x3d673cdb,0xbd623cf1,0x3c16bd7d,0xbcc43d6d,0xbd04bd5c,0x3d7f3bc9,0xbd2c3d3e,0x3d55bd0e,0xbb493d80,0xbd46bd22,0x3d78bc79,0xbd800000,0x3d18bd4e,0x3c953d75,0xbd71bcac,
0xbd0e3d55,0xbcacbd71,0x3d753c95,0xbd4e3d18,0x3d6dbcc4,0xbc793d78,0xbd22bd46,0x3d80bb49,0xbd7bbc48,0x3d3ebd2c,0x3bc93d7f,0xbd5cbd04,0x3d353d35,0xbd7d3c16,0x3cf1bd62,0x3cdb3d67,
0xbd35bd35,0x3d803b49,0xbd463d22,0x3c16bd7d,0x3d0e3d55,0xbd78bc79,0x3d62bcf1,0xbcac3d71,0xbcc4bd6d,0x3d673cdb,0xbd753c95,0x3d04bd5c,0x3c483d7b,0xbd4ebd18,0x3d7fbbc9,0xbd2c3d3e,
0xbd800000,0x3d3ebd2c,0xbbc93d7f,0xbd18bd4e,0x3d7b3c48,0xbd5c3d04,0x3c95bd75,0x3cdb3d67,0xbd6dbcc4,0x3d71bcac,0xbcf13d62,0xbc79bd78,0x3d553d0e,0xbd7d3c16,0x3d22bd46,0x3b493d80,
0x3c48bd7b,0x3cac3d71,0xbd46bd22,0x3d7d3c16,0x3d353d35,0xbd78bc79,0x3d75bc95,0xbd2c3d3e,0x3d553d0e,0xbd80bb49,0x3d62bcf1,0xbd043d5c,0xbd6d3cc4,0x3d18bd4e,0xbbc93d7f,0xbcdbbd67,
0x3d0e3d55,0xbd67bcdb,0x3d7fbbc9,0xbd4e3d18,0xbd800000,0x3d5cbd04,0xbcf13d62,0xbb49bd80,0xbd7b3c48,0x3d3ebd2c,0xbc953d75,0xbc79bd78,0x3cc4bd6d,0x3c163d7d,0xbd22bd46,0x3d713cac,
0x3cc43d6d,0xbd2cbd3e,0x3d623cf1,0xbd7dbc16,0x3d7bbc48,0xbd5c3d04,0x3d22bd46,0xbcac3d71,0xbd35bd35,0x3d673cdb,0xbd7fbbc9,0x3d78bc79,0xbd553d0e,0x3d18bd4e,0xbc953d75,0xbb49bd80,
0x3d6d3cc4,0xbd80bb49,0x3d75bc95,0xbd4e3d18,0x3d0ebd55,0xbc793d78,0xbbc9bd7f,0x3cdb3d67,0xbd800000,0x3d71bcac,0xbd463d22,0x3d04bd5c,0xbc483d7b,0xbc16bd7d,0x3cf13d62,0xbd3ebd2c,
0x3d0ebd55,0xbcdb3d67,0x3c95bd75,0xbc163d7d,0x3d6dbcc4,0xbd5c3d04,0x3d46bd22,0xbd2c3d3e,0x3d7b3c48,0xbd80bb49,0x3d7fbbc9,0xbd783c79,0x3d353d35,0xbd4ebd18,0x3d623cf1,0xbd71bcac,
0x3c483d7b,0xbcacbd71,0x3cf13d62,0xbd18bd4e,0xbcc43d6d,0x3c79bd78,0xbbc93d7f,0xbb49bd80,0xbd553d0e,0x3d3ebd2c,0xbd223d46,0x3d04bd5c,0xbd800000,0x3d7dbc16,0xbd753c95,0x3d67bcdb,
0x3d80,0x3b49bd80,0xbbc93d7f,0x3c16bd7d,0xbc483d7b,0x3c79bd78,0xbc953d75,0x3cacbd71,0xbcc43d6d,0x3cdbbd67,0xbcf13d62,0x3d04bd5c,0xbd0e3d55,0x3d18bd4e,0xbd223d46,0x3d2cbd3e,
0xbd353d35,0x3d3ebd2c,0xbd463d22,0x3d4ebd18,0xbd553d0e,0x3d5cbd04,0xbd623cf1,0x3d67bcdb,0xbd6d3cc4,0x3d71bcac,0xbd753c95,0x3d78bc79,0xbd7b3c48,0x3d7dbc16,0xbd7f3bc9,0x3d80bb49,
0xbd553d0e,0x3d71bcac,0xbd7f3bc9,0x3d7d3c16,0x3d80,0x3c79bd78,0xbcf13d62,0x3d2cbd3e,0xbc48bd7b,0xbb493d80,0x3c95bd75,0xbd043d5c,0xbd6dbcc4,0x3d4e3d18,0xbd22bd46,0x3cdb3d67,
0x3d7b3c48,0xbd67bcdb,0x3d463d22,0xbd18bd4e,0x3d35bd35,0xbd5c3d04,0x3d75bc95,0xbd803b49,0xbd0e3d55,0x3d3ebd2c,0xbd623cf1,0x3d78bc79,0x3cc43d6d,0xbc16bd7d,0xbbc93d7f,0x3cacbd71,
0x3cc4bd6d,0xbd3e3d2c,0x3d75bc95,0xbd7dbc16,0x3d553d0e,0xbd04bd5c,0x3bc93d7f,0x3cacbd71,0x3d80,0x3cdbbd67,0xbd463d22,0x3d78bc79,0xbd7bbc48,0x3d4e3d18,0xbcf1bd62,0x3b493d80,
0x3d6dbcc4,0xbd80bb49,0x3d623cf1,0xbd18bd4e,0x3c483d7b,0x3c79bd78,0xbd223d46,0x3d67bcdb,0xbd353d35,0x3d71bcac,0xbd7fbbc9,0x3d5c3d04,0xbd0ebd55,0x3c163d7d,0x3c95bd75,0xbd2c3d3e,
0xbd7b3c48,0x3d673cdb,0xbcf1bd62,0xbc163d7d,0x3d6d3cc4,0xbd04bd5c,0xbbc93d7f,0x3d2cbd3e,0xbd0ebd55,0xbb493d80,0x3d22bd46,0xbd783c79,0x3d80,0x3d18bd4e,0xbd753c95,0x3d713cac,
0x3d553d0e,0xbcacbd71,0xbc953d75,0x3d4ebd18,0xbcc4bd6d,0xbc793d78,0x3d46bd22,0xbd803b49,0xbc483d7b,0x3d3ebd2c,0xbd7f3bc9,0x3d5c3d04,0x3d35bd35,0xbd7d3c16,0x3d623cf1,0xbcdbbd67,
0xbd353d35,0x3d803b49,0xbd22bd46,0xbc163d7d,0x3d55bd0e,0xbd78bc79,0x3cf13d62,0x3cacbd71,0xbd6d3cc4,0x3d673cdb,0xbc95bd75,0xbd043d5c,0x3d7bbc48,0xbd4ebd18,0x3bc93d7f,0x3d2cbd3e,
0x3d80,0x3d3ebd2c,0xbd7fbbc9,0x3d183d4e,0x3c48bd7b,0xbd5c3d04,0x3d753c95,0xbcdbbd67,0xbcc43d6d,0x3d71bcac,0xbd62bcf1,0x3c793d78,0x3d0ebd55,0xbd7d3c16,0x3d463d22,0xbb49bd80,
0xbd7bbc48,0x3cac3d71,0x3d22bd46,0xbd7dbc16,0x3d35bd35,0xbd78bc79,0x3c953d75,0x3d2cbd3e,0x3d0ebd55,0xbd80bb49,0x3cf13d62,0x3d04bd5c,0x3cc43d6d,0x3d18bd4e,0xbd7fbbc9,0x3cdb3d67,
0x3d55bd0e,0xbd67bcdb,0x3bc93d7f,0x3d4ebd18,0x3d80,0x3d5cbd04,0xbd62bcf1,0x3b493d80,0x3c483d7b,0x3d3ebd2c,0xbd75bc95,0x3c793d78,0xbd6dbcc4,0x3c163d7d,0x3d46bd22,0xbd71bcac,
0x3d6dbcc4,0xbd2cbd3e,0xbcf13d62,0x3d7d3c16,0xbc48bd7b,0xbd5c3d04,0x3d463d22,0x3cacbd71,0xbd353d35,0x3d673cdb,0x3bc9bd7f,0xbd783c79,0x3d0e3d55,0x3d18bd4e,0xbd75bc95,0x3b493d80,
0x3cc4bd6d,0xbd80bb49,0x3c953d75,0x3d4ebd18,0xbd55bd0e,0xbc793d78,0x3d7fbbc9,0xbcdbbd67,0x3d80,0x3d71bcac,0xbd22bd46,0xbd043d5c,0x3d7b3c48,0xbc16bd7d,0xbd623cf1,0x3d3e3d2c,
0xbd55bd0e,0xbcdb3d67,0x3d753c95,0x3c16bd7d,0xbcc4bd6d,0xbd5c3d04,0x3d223d46,0x3d2cbd3e,0x3c48bd7b,0xbd80bb49,0x3bc93d7f,0x3d78bc79,0x3d35bd35,0xbd4ebd18,0xbcf13d62,0x3d713cac,
0x3d7bbc48,0xbcacbd71,0xbd623cf1,0x3d183d4e,0x3d6d3cc4,0x3c79bd78,0xbd7fbbc9,0x3b493d80,0x3d0e3d55,0x3d3ebd2c,0xbd46bd22,0xbd043d5c,0x3d80,0x3d7dbc16,0xbc95bd75,0xbd673cdb,
0xbd800000,0x3d803b49,0xbd7fbbc9,0x3d7d3c16,0xbd7bbc48,0x3d783c79,0xbd75bc95,0x3d713cac,0xbd6dbcc4,0x3d673cdb,0xbd62bcf1,0x3d5c3d04,0xbd55bd0e,0x3d4e3d18,0xbd46bd22,0x3d3e3d2c,
0xbd35bd35,0x3d2c3d3e,0xbd22bd46,0x3d183d4e,0xbd0ebd55,0x3d043d5c,0xbcf1bd62,0x3cdb3d67,0xbcc4bd6d,0x3cac3d71,0xbc95bd75,0x3c793d78,0xbc48bd7b,0x3c163d7d,0xbbc9bd7f,0x3b493d80,
0xbd0ebd55,0x3cac3d71,0xbbc9bd7f,0xbc163d7d,0xbd800000,0x3d783c79,0xbd62bcf1,0x3d3e3d2c,0x3d7bbc48,0xbd80bb49,0x3d753c95,0xbd5cbd04,0x3cc4bd6d,0xbd183d4e,0x3d46bd22,0xbd673cdb,
0xbc483d7b,0x3cdbbd67,0xbd223d46,0x3d4ebd18,0x3d353d35,0xbd04bd5c,0x3c953d75,0xbb49bd80,0xbd55bd0e,0x3d2c3d3e,0xbcf1bd62,0x3c793d78,0xbd6d3cc4,0x3d7dbc16,0xbd7fbbc9,0x3d713cac,
0x3d6d3cc4,0xbd2cbd3e,0x3c953d75,0x3c16bd7d,0xbd0e3d55,0x3d5cbd04,0xbd7f3bc9,0x3d713cac,0xbd800000,0x3d673cdb,0xbd22bd46,0x3c793d78,0x3c48bd7b,0xbd183d4e,0x3d62bcf1,0xbd803b49,
0x3cc43d6d,0x3b49bd80,0xbcf13d62,0x3d4ebd18,0xbd7b3c48,0x3d783c79,0xbd46bd22,0x3cdb3d67,0xbd35bd35,0x3cac3d71,0x3bc9bd7f,0xbd043d5c,0x3d55bd0e,0xbd7d3c16,0x3d753c95,0xbd3ebd2c,
0xbc48bd7b,0xbcdb3d67,0x3d62bcf1,0xbd7dbc16,0xbcc43d6d,0x3d5cbd04,0xbd7fbbc9,0x3d3e3d2c,0x3d55bd0e,0xbd80bb49,0x3d463d22,0xbc79bd78,0xbd800000,0x3d4e3d18,0xbc95bd75,0xbcac3d71,
0xbd0e3d55,0x3d71bcac,0xbd75bc95,0x3d183d4e,0x3d6dbcc4,0xbd78bc79,0x3d223d46,0xbb49bd80,0xbd7bbc48,0x3d2c3d3e,0xbbc9bd7f,0xbd043d5c,0x3d353d35,0xbc16bd7d,0xbcf13d62,0x3d67bcdb,
0xbd35bd35,0xbb493d80,0x3d46bd22,0xbd7dbc16,0x3d0e3d55,0x3c79bd78,0xbd623cf1,0x3d713cac,0xbcc4bd6d,0xbcdb3d67,0x3d75bc95,0xbd5cbd04,0x3c483d7b,0x3d18bd4e,0xbd7f3bc9,0x3d3e3d2c,
0xbd800000,0x3d2c3d3e,0x3bc9bd7f,0xbd4e3d18,0x3d7b3c48,0xbd04bd5c,0xbc953d75,0x3d67bcdb,0xbd6dbcc4,0x3cac3d71,0x3cf1bd62,0xbd783c79,0x3d553d0e,0xbc16bd7d,0xbd223d46,0x3d80bb49,
0x3c48bd7b,0xbd713cac,0x3d463d22,0x3c16bd7d,0x3d353d35,0x3c79bd78,0xbd753c95,0x3d3e3d2c,0x3d553d0e,0x3b49bd80,0xbd623cf1,0x3d5c3d04,0xbd6d3cc4,0x3d4e3d18,0x3bc9bd7f,0xbd673cdb,
0x3d0e3d55,0x3cdbbd67,0xbd7f3bc9,0x3d183d4e,0xbd800000,0x3d043d5c,0x3cf1bd62,0xbd803b49,0xbd7b3c48,0x3d2c3d3e,0x3c95bd75,0xbd783c79,0x3cc4bd6d,0xbd7d3c16,0x3d223d46,0x3cacbd71,
0x3cc43d6d,0x3d3ebd2c,0xbd62bcf1,0xbc163d7d,0x3d7bbc48,0xbd04bd5c,0xbd223d46,0x3d713cac,0xbd35bd35,0xbcdb3d67,0x3d7f3bc9,0xbc79bd78,0xbd553d0e,0x3d4e3d18,0x3c95bd75,0xbd803b49,
0x3d6d3cc4,0x3b49bd80,0xbd753c95,0x3d183d4e,0x3d0ebd55,0xbd78bc79,0x3bc93d7f,0x3d67bcdb,0xbd800000,0x3cac3d71,0x3d46bd22,0xbd5cbd04,0xbc483d7b,0x3d7dbc16,0xbcf1bd62,0xbd2c3d3e,
0x3d0ebd55,0xbd67bcdb,0xbc953d75,0x3d7d3c16,0x3d6dbcc4,0xbd04bd5c,0xbd463d22,0x3d3e3d2c,0x3d7b3c48,0x3b49bd80,0xbd7f3bc9,0x3c793d78,0x3d353d35,0x3d18bd4e,0xbd62bcf1,0xbcac3d71,
0x3c483d7b,0x3d71bcac,0xbcf1bd62,0xbd4e3d18,0xbcc43d6d,0x3d783c79,0x3bc9bd7f,0xbd803b49,0xbd553d0e,0x3d2c3d3e,0x3d22bd46,0xbd5cbd04,0xbd800000,0x3c163d7d,0x3d75bc95,0xbcdbbd67,
0x3d80,0x3d803b49,0x3bc9bd7f,0xbd7dbc16,0xbc483d7b,0x3d783c79,0x3c95bd75,0xbd71bcac,0xbcc43d6d,0x3d673cdb,0x3cf1bd62,0xbd5cbd04,0xbd0e3d55,0x3d4e3d18,0x3d22bd46,0xbd3ebd2c,
0xbd353d35,0x3d2c3d3e,0x3d46bd22,0xbd18bd4e,0xbd553d0e,0x3d043d5c,0x3d62bcf1,0xbcdbbd67,0xbd6d3cc4,0x3cac3d71,0x3d75bc95,0xbc79bd78,0xbd7b3c48,0x3c163d7d,0x3d7fbbc9,0xbb49bd80,
0xbd553d0e,0x3cac3d71,0x3d7fbbc9,0x3c16bd7d,0x3d80,0x3d783c79,0x3cf1bd62,0xbd3ebd2c,0xbc48bd7b,0xbd80bb49,0xbc953d75,0x3d5c3d04,0xbd6dbcc4,0xbd183d4e,0x3d223d46,0x3d67bcdb,
0x3d7b3c48,0x3cdbbd67,0xbd46bd22,0xbd4e3d18,0x3d35bd35,0xbd04bd5c,0xbd753c95,0x3b493d80,0xbd0e3d55,0x3d2c3d3e,0x3d62bcf1,0xbc79bd78,0x3cc43d6d,0x3d7dbc16,0x3bc9bd7f,0xbd71bcac,
0x3cc4bd6d,0xbd2cbd3e,0xbd753c95,0xbc163d7d,0x3d553d0e,0x3d5cbd04,0xbbc9bd7f,0xbd71bcac,0x3d80,0x3d673cdb,0x3d46bd22,0xbc79bd78,0xbd7bbc48,0xbd183d4e,0x3cf13d62,0x3d80bb49,
0x3d6dbcc4,0x3b49bd80,0xbd62bcf1,0xbd4e3d18,0x3c483d7b,0x3d783c79,0x3d22bd46,0xbcdbbd67,0xbd353d35,0x3cac3d71,0x3d7f3bc9,0x3d04bd5c,0xbd0ebd55,0xbd7d3c16,0xbc953d75,0x3d3e3d2c,
0xbd7b3c48,0xbcdb3d67,0x3cf13d62,0x3d7d3c16,0x3d6d3cc4,0x3d5cbd04,0x3bc9bd7f,0xbd3ebd2c,0xbd0ebd55,0xbd80bb49,0xbd223d46,0x3c793d78,0x3d80,0x3d4e3d18,0x3d75bc95,0x3cacbd71,
0x3d553d0e,0x3d71bcac,0x3c95bd75,0xbd18bd4e,0xbcc4bd6d,0xbd78bc79,0xbd463d22,0x3b493d80,0xbc483d7b,0x3d2c3d3e,0x3d7fbbc9,0x3d04bd5c,0x3d35bd35,0xbc16bd7d,0xbd62bcf1,0xbd673cdb,
0xbd353d35,0xbb493d80,0x3d223d46,0x3d7d3c16,0x3d55bd0e,0x3c79bd78,0xbcf1bd62,0xbd71bcac,0xbd6d3cc4,0xbcdb3d67,0x3c953d75,0x3d5c3d04,0x3d7bbc48,0x3d18bd4e,0xbbc9bd7f,0xbd3ebd2c,
0x3d80,0x3d2c3d3e,0x3d7f3bc9,0x3d4ebd18,0x3c48bd7b,0xbd04bd5c,0xbd75bc95,0xbd673cdb,0xbcc43d6d,0x3cac3d71,0x3d623cf1,0x3d78bc79,0x3d0ebd55,0xbc16bd7d,0xbd46bd22,0xbd803b49,
0xbd7bbc48,0xbd713cac,0xbd223d46,0xbc163d7d,0x3d35bd35,0x3c79bd78,0xbc95bd75,0xbd3ebd2c,0x3d0ebd55,0x3b49bd80,0xbcf1bd62,0xbd5cbd04,0x3cc43d6d,0x3d4e3d18,0x3d7f3bc9,0x3d67bcdb,
0x3d55bd0e,0x3cdbbd67,0xbbc9bd7f,0xbd18bd4e,0x3d80,0x3d043d5c,0x3d623cf1,0x3d80bb49,0x3c483d7b,0x3d2c3d3e,0x3d753c95,0x3d78bc79,0xbd6dbcc4,0xbd7d3c16,0xbd463d22,0xbcac3d71,
0x3d6dbcc4,0x3d3ebd2c,0x3cf1bd62,0x3c16bd7d,0xbc48bd7b,0xbd04bd5c,0xbd46bd22,0xbd71bcac,0xbd353d35,0xbcdb3d67,0xbbc93d7f,0x3c793d78,0x3d0e3d55,0x3d4e3d18,0x3d753c95,0x3d80bb49,
0x3cc4bd6d,0x3b49bd80,0xbc95bd75,0xbd18bd4e,0xbd55bd0e,0xbd78bc79,0xbd7f3bc9,0xbd673cdb,0x3d80,0x3cac3d71,0x3d223d46,0x3d5c3d04,0x3d7b3c48,0x3d7dbc16,0x3d62bcf1,0x3d2cbd3e,
0xbd55bd0e,0xbd67bcdb,0xbd75bc95,0xbd7dbc16,0xbcc4bd6d,0xbd04bd5c,0xbd22bd46,0xbd3ebd2c,0x3c48bd7b,0x3b49bd80,0xbbc9bd7f,0xbc79bd78,0x3d35bd35,0x3d18bd4e,0x3cf1bd62,0x3cacbd71,
0x3d7bbc48,0x3d71bcac,0x3d62bcf1,0x3d4ebd18,0x3d6d3cc4,0x3d783c79,0x3d7f3bc9,0x3d80bb49,0x3d0e3d55,0x3d2c3d3e,0x3d463d22,0x3d5c3d04,0x3d80,0x3c163d7d,0x3c953d75,0x3cdb3d67,
0xbd800000,0xbb493d80,0x3d7f3bc9,0x3c16bd7d,0xbd7bbc48,0xbc793d78,0x3d753c95,0x3cacbd71,0xbd6dbcc4,0xbcdb3d67,0x3d623cf1,0x3d04bd5c,0xbd55bd0e,0xbd183d4e,0x3d463d22,0x3d2cbd3e,
0xbd35bd35,0xbd3e3d2c,0x3d223d46,0x3d4ebd18,0xbd0ebd55,0xbd5c3d04,0x3cf13d62,0x3d67bcdb,0xbcc4bd6d,0xbd713cac,0x3c953d75,0x3d78bc79,0xbc48bd7b,0xbd7d3c16,0x3bc93d7f,0x3d80bb49,
0xbd0ebd55,0xbd713cac,0x3bc93d7f,0x3d7d3c16,0xbd800000,0xbc793d78,0x3d623cf1,0x3d2cbd3e,0x3d7bbc48,0x3b49bd80,0xbd75bc95,0xbd043d5c,0x3cc4bd6d,0xbd4ebd18,0xbd463d22,0x3cdb3d67,
0xbc483d7b,0x3d673cdb,0x3d22bd46,0xbd18bd4e,0x3d353d35,0x3d5cbd04,0xbc95bd75,0xbd803b49,0xbd55bd0e,0xbd3e3d2c,0x3cf13d62,0x3d78bc79,0xbd6d3cc4,0x3c163d7d,0x3d7f3bc9,0x3cacbd71,
0x3d6d3cc4,0x3d3ebd2c,0xbc95bd75,0xbd7dbc16,0xbd0e3d55,0x3d043d5c,0x3d7fbbc9,0x3cacbd71,0xbd800000,0xbcdb3d67,0x3d223d46,0x3d78bc79,0x3c48bd7b,0xbd4ebd18,0xbd623cf1,0x3b493d80,
0x3cc43d6d,0x3d803b49,0x3cf1bd62,0xbd18bd4e,0xbd7b3c48,0xbc793d78,0x3d463d22,0x3d67bcdb,0xbd35bd35,0xbd713cac,0xbbc93d7f,0x3d5c3d04,0x3d55bd0e,0xbc16bd7d,0xbd75bc95,0xbd2c3d3e,
0xbc48bd7b,0xbd67bcdb,0xbd623cf1,0xbc163d7d,0xbcc43d6d,0x3d043d5c,0x3d7f3bc9,0x3d2cbd3e,0x3d55bd0e,0x3b49bd80,0xbd46bd22,0xbd783c79,0xbd800000,0xbd183d4e,0x3c953d75,0x3d713cac,
0xbd0e3d55,0x3cac3d71,0x3d753c95,0x3d4ebd18,0x3d6dbcc4,0x3c79bd78,0xbd22bd46,0xbd803b49,0xbd7bbc48,0xbd3e3d2c,0x3bc93d7f,0x3d5c3d04,0x3d353d35,0x3d7dbc16,0x3cf1bd62,0xbcdbbd67,
0xbd35bd35,0xbd80bb49,0xbd463d22,0xbc163d7d,0x3d0e3d55,0x3d783c79,0x3d62bcf1,0x3cacbd71,0xbcc4bd6d,0xbd67bcdb,0xbd753c95,0xbd043d5c,0x3c483d7b,0x3d4e3d18,0x3d7fbbc9,0x3d2cbd3e,
0xbd800000,0xbd3e3d2c,0xbbc93d7f,0x3d183d4e,0x3d7b3c48,0x3d5cbd04,0x3c95bd75,0xbcdbbd67,0xbd6dbcc4,0xbd713cac,0xbcf13d62,0x3c793d78,0x3d553d0e,0x3d7dbc16,0x3d22bd46,0xbb49bd80,
0x3c48bd7b,0xbcacbd71,0xbd46bd22,0xbd7dbc16,0x3d353d35,0x3d783c79,0x3d75bc95,0x3d2cbd3e,0x3d553d0e,0x3d803b49,0x3d62bcf1,0x3d04bd5c,0xbd6d3cc4,0xbd183d4e,0xbbc93d7f,0x3cdb3d67,
0x3d0e3d55,0x3d673cdb,0x3d7fbbc9,0x3d4ebd18,0xbd800000,0xbd5c3d04,0xbcf13d62,0x3b493d80,0xbd7b3c48,0xbd3e3d2c,0xbc953d75,0x3c793d78,0x3cc4bd6d,0xbc16bd7d,0xbd22bd46,0xbd71bcac,
0x3cc43d6d,0x3d2c3d3e,0x3d623cf1,0x3d7d3c16,0x3d7bbc48,0x3d5cbd04,0x3d22bd46,0x3cacbd71,0xbd35bd35,0xbd67bcdb,0xbd7fbbc9,0xbd783c79,0xbd553d0e,0xbd183d4e,0xbc953d75,0x3b493d80,
0x3d6d3cc4,0x3d803b49,0x3d75bc95,0x3d4ebd18,0x3d0ebd55,0x3c79bd78,0xbbc9bd7f,0xbcdbbd67,0xbd800000,0xbd713cac,0xbd463d22,0xbd043d5c,0xbc483d7b,0x3c163d7d,0x3cf13d62,0x3d3e3d2c,
0x3d0ebd55,0x3cdbbd67,0x3c95bd75,0x3c16bd7d,0x3d6dbcc4,0x3d5cbd04,0x3d46bd22,0x3d2cbd3e,0x3d7b3c48,0x3d803b49,0x3d7fbbc9,0x3d78bc79,0x3d353d35,0x3d4e3d18,0x3d623cf1,0x3d713cac,
0x3c483d7b,0x3cac3d71,0x3cf13d62,0x3d183d4e,0xbcc43d6d,0xbc793d78,0xbbc93d7f,0x3b493d80,0xbd553d0e,0xbd3e3d2c,0xbd223d46,0xbd043d5c,0xbd800000,0xbd7d3c16,0xbd753c95,0xbd673cdb,
0x3d80,0xbbc93d7f,0xbc483d7b,0xbc953d75,0xbcc43d6d,0xbcf13d62,0xbd0e3d55,0xbd223d46,0xbd353d35,0xbd463d22,0xbd553d0e,0xbd623cf1,0xbd6d3cc4,0xbd753c95,0xbd7b3c48,0xbd7f3bc9,
0xbd800000,0xbd7fbbc9,0xbd7bbc48,0xbd75bc95,0xbd6dbcc4,0xbd62bcf1,0xbd55bd0e,0xbd46bd22,0xbd35bd35,0xbd22bd46,0xbd0ebd55,0xbcf1bd62,0xbcc4bd6d,0xbc95bd75,0xbc48bd7b,0xbbc9bd7f,
0xbd6d3cc4,0xbd7f3bc9,0xbd7bbc48,0xbd62bcf1,0x3d80,0xbc953d75,0xbd0e3d55,0xbd463d22,0x3cc4bd6d,0x3d22bd46,0x3d55bd0e,0x3d75bc95,0xbd35bd35,0xbcf1bd62,0xbc48bd7b,0x3bc9bd7f,
0x3cc43d6d,0x3bc93d7f,0xbc483d7b,0xbcf13d62,0x3d800000,0x3d753c95,0x3d553d0e,0x3d223d46,0xbd6dbcc4,0xbd46bd22,0xbd0ebd55,0xbc95bd75,0xbd353d35,0xbd623cf1,0xbd7b3c48,0xbd7fbbc9,
0x3d35bd35,0x3d75bc95,0x3d7b3c48,0x3d463d22,0x3cc43d6d,0xbbc93d7f,0xbd0e3d55,0xbd623cf1,0x3d80,0xbcf13d62,0xbd553d0e,0xbd7f3bc9,0xbd6dbcc4,0xbd22bd46,0xbc48bd7b,0x3c95bd75,
0x3d353d35,0x3c953d75,0xbc483d7b,0xbd223d46,0xbd6d3cc4,0xbd7fbbc9,0xbd55bd0e,0xbcf1bd62,0xbd800000,0xbd62bcf1,0xbd0ebd55,0xbbc9bd7f,0x3cc4bd6d,0x3d46bd22,0x3d7bbc48,0x3d753c95,
0xbd6dbcc4,0xbcf1bd62,0x3c48bd7b,0x3d46bd22,0x3d353d35,0x3bc93d7f,0xbd0e3d55,0xbd753c95,0xbcc4bd6d,0x3c95bd75,0x3d55bd0e,0x3d7f3bc9,0x3d80,0xbd223d46,0xbd7b3c48,0xbd62bcf1,
0xbcc43d6d,0xbd623cf1,0xbd7bbc48,0xbd22bd46,0x3d35bd35,0x3d7fbbc9,0x3d553d0e,0x3c953d75,0xbd6d3cc4,0xbd75bc95,0xbd0ebd55,0x3bc9bd7f,0x3d800000,0x3d463d22,0x3c483d7b,0xbcf13d62,
0xbd800000,0xbd22bd46,0x3c48bd7b,0x3d62bcf1,0x3d6d3cc4,0x3c953d75,0xbd0e3d55,0xbd7f3bc9,0xbd35bd35,0x3bc9bd7f,0x3d55bd0e,0x3d753c95,0x3cc43d6d,0xbcf13d62,0xbd7b3c48,0xbd46bd22,
0x3d80,0xbd463d22,0xbd7bbc48,0xbcf1bd62,0x3cc4bd6d,0x3d75bc95,0x3d553d0e,0x3bc93d7f,0xbd353d35,0xbd7fbbc9,0xbd0ebd55,0x3c95bd75,0x3d6dbcc4,0x3d623cf1,0x3c483d7b,0xbd223d46,
0xbcc4bd6d,0x3d22bd46,0x3d7b3c48,0x3c953d75,0x3d800000,0x3cf13d62,0xbd0e3d55,0xbd7fbbc9,0x3d6d3cc4,0x3bc93d7f,0xbd553d0e,0xbd62bcf1,0xbd353d35,0xbd75bc95,0xbc48bd7b,0x3d46bd22,
0x3d6dbcc4,0x3d463d22,0xbc483d7b,0xbd753c95,0x3d80,0xbd623cf1,0xbd55bd0e,0x3bc9bd7f,0xbcc43d6d,0xbd7f3bc9,0xbd0ebd55,0x3cf1bd62,0xbd35bd35,0x3c95bd75,0x3d7bbc48,0x3d223d46,
0x3d353d35,0xbcf13d62,0xbd7bbc48,0xbbc9bd7f,0x3d6dbcc4,0x3d223d46,0xbd0e3d55,0xbd75bc95,0xbd800000,0xbc95bd75,0x3d55bd0e,0x3d463d22,0xbcc43d6d,0xbd7fbbc9,0xbc48bd7b,0x3d62bcf1,
0x3d35bd35,0x3d623cf1,0xbc483d7b,0xbd7f3bc9,0xbcc4bd6d,0x3d46bd22,0x3d553d0e,0xbc953d75,0x3d80,0xbd753c95,0xbd0ebd55,0x3d22bd46,0x3d6d3cc4,0xbbc93d7f,0xbd7b3c48,0xbcf1bd62,
0x3cc4bd6d,0x3d753c95,0xbc483d7b,0xbd7fbbc9,0x3d35bd35,0x3d463d22,0xbd0e3d55,0xbd62bcf1,0x3d6dbcc4,0x3cf13d62,0xbd553d0e,0xbd22bd46,0x3d800000,0x3bc93d7f,0xbd7b3c48,0xbc95bd75,
0x3d6d3cc4,0xbc953d75,0xbd7bbc48,0x3bc9bd7f,0x3d353d35,0xbd223d46,0xbd55bd0e,0x3cf1bd62,0x3cc43d6d,0xbd623cf1,0xbd0ebd55,0x3d46bd22,0x3d80,0xbd7f3bc9,0xbc48bd7b,0x3d75bc95,
0xbd800000,0xbd7fbbc9,0xbd7bbc48,0xbd75bc95,0xbd6dbcc4,0xbd62bcf1,0xbd55bd0e,0xbd46bd22,0xbd35bd35,0xbd22bd46,0xbd0ebd55,0xbcf1bd62,0xbcc4bd6d,0xbc95bd75,0xbc48bd7b,0xbbc9bd7f,
0x8000bd80,0x3bc9bd7f,0x3c48bd7b,0x3c95bd75,0x3cc4bd6d,0x3cf1bd62,0x3d0ebd55,0x3d22bd46,0x3d35bd35,0x3d46bd22,0x3d55bd0e,0x3d62bcf1,0x3d6dbcc4,0x3d75bc95,0x3d7bbc48,0x3d7fbbc9,
0xbcc4bd6d,0xbbc9bd7f,0x3c48bd7b,0x3cf1bd62,0xbd800000,0xbd75bc95,0xbd55bd0e,0xbd22bd46,0x3d6d3cc4,0x3d463d22,0x3d0e3d55,0x3c953d75,0x3d35bd35,0x3d62bcf1,0x3d7bbc48,0x3d7f3bc9,
0xbd6d3cc4,0xbd7f3bc9,0xbd7bbc48,0xbd62bcf1,0x80003d80,0xbc953d75,0xbd0e3d55,0xbd463d22,0x3cc4bd6d,0x3d22bd46,0x3d55bd0e,0x3d75bc95,0xbd35bd35,0xbcf1bd62,0xbc48bd7b,0x3bc9bd7f,
0x3d353d35,0x3c953d75,0xbc483d7b,0xbd223d46,0xbd6d3cc4,0xbd7fbbc9,0xbd55bd0e,0xbcf1bd62,0xbd800000,0xbd62bcf1,0xbd0ebd55,0xbbc9bd7f,0x3cc4bd6d,0x3d46bd22,0x3d7bbc48,0x3d753c95,
0xbd353d35,0xbd753c95,0xbd7bbc48,0xbd46bd22,0xbcc4bd6d,0x3bc9bd7f,0x3d0ebd55,0x3d62bcf1,0x8000bd80,0x3cf1bd62,0x3d55bd0e,0x3d7fbbc9,0x3d6d3cc4,0x3d223d46,0x3c483d7b,0xbc953d75,
0x3cc4bd6d,0x3d62bcf1,0x3d7b3c48,0x3d223d46,0xbd353d35,0xbd7f3bc9,0xbd55bd0e,0xbc95bd75,0x3d6dbcc4,0x3d753c95,0x3d0e3d55,0xbbc93d7f,0xbd800000,0xbd46bd22,0xbc48bd7b,0x3cf1bd62,
0xbd6dbcc4,0xbcf1bd62,0x3c48bd7b,0x3d46bd22,0x3d353d35,0x3bc93d7f,0xbd0e3d55,0xbd753c95,0xbcc4bd6d,0x3c95bd75,0x3d55bd0e,0x3d7f3bc9,0x80003d80,0xbd223d46,0xbd7b3c48,0xbd62bcf1,
0x8000bd80,0x3d46bd22,0x3d7b3c48,0x3cf13d62,0xbcc43d6d,0xbd753c95,0xbd55bd0e,0xbbc9bd7f,0x3d35bd35,0x3d7f3bc9,0x3d0e3d55,0xbc953d75,0xbd6d3cc4,0xbd62bcf1,0xbc48bd7b,0x3d22bd46,
0xbd800000,0xbd22bd46,0x3c48bd7b,0x3d62bcf1,0x3d6d3cc4,0x3c953d75,0xbd0e3d55,0xbd7f3bc9,0xbd35bd35,0x3bc9bd7f,0x3d55bd0e,0x3d753c95,0x3cc43d6d,0xbcf13d62,0xbd7b3c48,0xbd46bd22,
0x3d6dbcc4,0x3d463d22,0xbc483d7b,0xbd753c95,0x80003d80,0xbd623cf1,0xbd55bd0e,0x3bc9bd7f,0xbcc43d6d,0xbd7f3bc9,0xbd0ebd55,0x3cf1bd62,0xbd35bd35,0x3c95bd75,0x3d7bbc48,0x3d223d46,
0x3cc43d6d,0xbd223d46,0xbd7bbc48,0xbc95bd75,0xbd800000,0xbcf1bd62,0x3d0ebd55,0x3d7f3bc9,0xbd6dbcc4,0xbbc9bd7f,0x3d55bd0e,0x3d623cf1,0x3d35bd35,0x3d753c95,0x3c483d7b,0xbd463d22,
0xbd353d35,0xbd62bcf1,0x3c48bd7b,0x3d7fbbc9,0x3cc43d6d,0xbd463d22,0xbd55bd0e,0x3c95bd75,0x8000bd80,0x3d75bc95,0x3d0e3d55,0xbd223d46,0xbd6dbcc4,0x3bc9bd7f,0x3d7bbc48,0x3cf13d62,
0x3d353d35,0xbcf13d62,0xbd7bbc48,0xbbc9bd7f,0x3d6dbcc4,0x3d223d46,0xbd0e3d55,0xbd75bc95,0xbd800000,0xbc95bd75,0x3d55bd0e,0x3d463d22,0xbcc43d6d,0xbd7fbbc9,0xbc48bd7b,0x3d62bcf1,
0x3d6d3cc4,0xbc953d75,0xbd7bbc48,0x3bc9bd7f,0x3d353d35,0xbd223d46,0xbd55bd0e,0x3cf1bd62,0x3cc43d6d,0xbd623cf1,0xbd0ebd55,0x3d46bd22,0x80003d80,0xbd7f3bc9,0xbc48bd7b,0x3d75bc95,
0xbcc43d6d,0xbd75bc95,0x3c48bd7b,0x3d7f3bc9,0xbd353d35,0xbd46bd22,0x3d0ebd55,0x3d623cf1,0xbd6d3cc4,0xbcf1bd62,0x3d55bd0e,0x3d223d46,0xbd800000,0xbbc9bd7f,0x3d7bbc48,0x3c953d75,
0x3d80,0xbd7fbbc9,0x3c48bd7b,0x3d753c95,0xbcc43d6d,0xbd62bcf1,0x3d0ebd55,0x3d463d22,0xbd353d35,0xbd22bd46,0x3d55bd0e,0x3cf13d62,0xbd6d3cc4,0xbc95bd75,0x3d7bbc48,0x3bc93d7f,
0xbd800000,0x3bc9bd7f,0x3d7b3c48,0xbc953d75,0xbd6dbcc4,0x3cf1bd62,0x3d553d0e,0xbd223d46,0xbd35bd35,0x3d46bd22,0x3d0e3d55,0xbd623cf1,0xbcc4bd6d,0x3d75bc95,0x3c483d7b,0xbd7f3bc9,
0xbd6d3cc4,0xbbc9bd7f,0x3d7b3c48,0xbcf13d62,0x3d80,0xbd75bc95,0x3d0ebd55,0x3d223d46,0x3cc4bd6d,0x3d463d22,0xbd553d0e,0xbc95bd75,0xbd35bd35,0x3d62bcf1,0x3c483d7b,0xbd7fbbc9,
0x3cc43d6d,0xbd7f3bc9,0x3c48bd7b,0x3d623cf1,0x3d800000,0xbc953d75,0xbd55bd0e,0x3d46bd22,0xbd6dbcc4,0x3d22bd46,0x3d0e3d55,0xbd753c95,0xbd353d35,0xbcf1bd62,0x3d7bbc48,0xbbc93d7f,
0x3d35bd35,0x3c953d75,0xbd7bbc48,0x3d22bd46,0x3cc43d6d,0xbd7fbbc9,0x3d0ebd55,0x3cf13d62,0x3d80,0xbd62bcf1,0x3d55bd0e,0x3bc93d7f,0xbd6dbcc4,0x3d46bd22,0x3c483d7b,0xbd75bc95,
0x3d353d35,0xbd753c95,0x3c48bd7b,0x3d463d22,0xbd6d3cc4,0x3bc9bd7f,0x3d553d0e,0xbd623cf1,0xbd800000,0x3cf1bd62,0x3d0e3d55,0xbd7f3bc9,0x3cc4bd6d,0x3d223d46,0xbd7b3c48,0x3c95bd75,
0xbd6dbcc4,0x3d62bcf1,0xbc483d7b,0xbd22bd46,0x3d353d35,0xbd7f3bc9,0x3d0ebd55,0x3c953d75,0xbcc4bd6d,0x3d753c95,0xbd553d0e,0x3bc9bd7f,0x3d80,0xbd46bd22,0x3d7bbc48,0xbcf13d62,
0xbcc43d6d,0xbcf1bd62,0x3d7b3c48,0xbd463d22,0x3d35bd35,0x3bc93d7f,0xbd55bd0e,0x3d75bc95,0xbd6d3cc4,0x3c95bd75,0x3d0e3d55,0xbd7fbbc9,0x3d800000,0xbd223d46,0xbc48bd7b,0x3d623cf1,
0xbd800000,0x3d46bd22,0xbc483d7b,0xbcf1bd62,0x3d6d3cc4,0xbd753c95,0x3d0ebd55,0x3bc93d7f,0xbd35bd35,0x3d7f3bc9,0xbd553d0e,0x3c95bd75,0x3cc43d6d,0xbd62bcf1,0x3d7bbc48,0xbd223d46,
0x3d80,0xbd22bd46,0x3d7b3c48,0xbd623cf1,0x3cc4bd6d,0x3c953d75,0xbd55bd0e,0x3d7fbbc9,0xbd353d35,0x3bc9bd7f,0x3d0e3d55,0xbd75bc95,0x3d6dbcc4,0xbcf13d62,0xbc48bd7b,0x3d463d22,
0xbcc4bd6d,0x3d463d22,0xbd7bbc48,0x3d75bc95,0x3d800000,0xbd623cf1,0x3d0ebd55,0xbbc93d7f,0x3d6d3cc4,0xbd7f3bc9,0x3d55bd0e,0xbcf13d62,0xbd353d35,0x3c95bd75,0x3c483d7b,0xbd22bd46,
0x3d6dbcc4,0xbd223d46,0x3c48bd7b,0x3c953d75,0x3d80,0xbcf1bd62,0x3d553d0e,0xbd7fbbc9,0xbcc43d6d,0xbbc9bd7f,0x3d0e3d55,0xbd62bcf1,0xbd35bd35,0x3d753c95,0xbd7b3c48,0x3d46bd22,
0x3d353d35,0xbd62bcf1,0x3d7b3c48,0xbd7f3bc9,0x3d6dbcc4,0xbd463d22,0x3d0ebd55,0xbc953d75,0xbd800000,0x3d75bc95,0xbd553d0e,0x3d22bd46,0xbcc43d6d,0x3bc9bd7f,0x3c483d7b,0xbcf1bd62,
0x3d35bd35,0xbcf13d62,0x3c48bd7b,0x3bc93d7f,0xbcc4bd6d,0x3d223d46,0xbd55bd0e,0x3d753c95,0x3d80,0xbc95bd75,0x3d0e3d55,0xbd46bd22,0x3d6d3cc4,0xbd7fbbc9,0x3d7bbc48,0xbd623cf1,
0x3cc4bd6d,0xbc953d75,0x3c48bd7b,0xbbc93d7f,0x3d35bd35,0xbd223d46,0x3d0ebd55,0xbcf13d62,0x3d6dbcc4,0xbd623cf1,0x3d55bd0e,0xbd463d22,0x3d800000,0xbd7f3bc9,0x3d7bbc48,0xbd753c95,
0x3d6d3cc4,0xbd75bc95,0x3d7b3c48,0xbd7fbbc9,0x3d353d35,0xbd46bd22,0x3d553d0e,0xbd62bcf1,0x3cc43d6d,0xbcf1bd62,0x3d0e3d55,0xbd22bd46,0x3d80,0xbbc9bd7f,0x3c483d7b,0xbc95bd75,
0xbd800000,0x3bc9bd7f,0x3d7b3c48,0xbc953d75,0xbd6dbcc4,0x3cf1bd62,0x3d553d0e,0xbd223d46,0xbd35bd35,0x3d46bd22,0x3d0e3d55,0xbd623cf1,0xbcc4bd6d,0x3d75bc95,0x3c483d7b,0xbd7f3bc9,
0x8000bd80,0x3d7f3bc9,0xbc483d7b,0xbd75bc95,0x3cc4bd6d,0x3d623cf1,0xbd0e3d55,0xbd46bd22,0x3d35bd35,0x3d223d46,0xbd553d0e,0xbcf1bd62,0x3d6dbcc4,0x3c953d75,0xbd7b3c48,0xbbc9bd7f,
0xbcc4bd6d,0x3d7fbbc9,0xbc483d7b,0xbd62bcf1,0xbd800000,0x3c95bd75,0x3d553d0e,0xbd463d22,0x3d6d3cc4,0xbd223d46,0xbd0ebd55,0x3d75bc95,0x3d35bd35,0x3cf13d62,0xbd7b3c48,0x3bc9bd7f,
0xbd6d3cc4,0xbbc9bd7f,0x3d7b3c48,0xbcf13d62,0x80003d80,0xbd75bc95,0x3d0ebd55,0x3d223d46,0x3cc4bd6d,0x3d463d22,0xbd553d0e,0xbc95bd75,0xbd35bd35,0x3d62bcf1,0x3c483d7b,0xbd7fbbc9,
0x3d353d35,0xbd753c95,0x3c48bd7b,0x3d463d22,0xbd6d3cc4,0x3bc9bd7f,0x3d553d0e,0xbd623cf1,0xbd800000,0x3cf1bd62,0x3d0e3d55,0xbd7f3bc9,0x3cc4bd6d,0x3d223d46,0xbd7b3c48,0x3c95bd75,
0xbd353d35,0xbc95bd75,0x3d7b3c48,0xbd223d46,0xbcc4bd6d,0x3d7f3bc9,0xbd0e3d55,0xbcf1bd62,0x8000bd80,0x3d623cf1,0xbd553d0e,0xbbc9bd7f,0x3d6d3cc4,0xbd463d22,0xbc48bd7b,0x3d753c95,
0x3cc4bd6d,0x3cf13d62,0xbd7bbc48,0x3d46bd22,0xbd353d35,0xbbc9bd7f,0x3d553d0e,0xbd753c95,0x3d6dbcc4,0xbc953d75,0xbd0ebd55,0x3d7f3bc9,0xbd800000,0x3d22bd46,0x3c483d7b,0xbd62bcf1,
0xbd6dbcc4,0x3d62bcf1,0xbc483d7b,0xbd22bd46,0x3d353d35,0xbd7f3bc9,0x3d0ebd55,0x3c953d75,0xbcc4bd6d,0x3d753c95,0xbd553d0e,0x3bc9bd7f,0x80003d80,0xbd46bd22,0x3d7bbc48,0xbcf13d62,
0x8000bd80,0x3d223d46,0xbd7bbc48,0x3d62bcf1,0xbcc43d6d,0xbc95bd75,0x3d553d0e,0xbd7f3bc9,0x3d35bd35,0xbbc93d7f,0xbd0ebd55,0x3d753c95,0xbd6d3cc4,0x3cf1bd62,0x3c483d7b,0xbd46bd22,
0xbd800000,0x3d46bd22,0xbc483d7b,0xbcf1bd62,0x3d6d3cc4,0xbd753c95,0x3d0ebd55,0x3bc93d7f,0xbd35bd35,0x3d7f3bc9,0xbd553d0e,0x3c95bd75,0x3cc43d6d,0xbd62bcf1,0x3d7bbc48,0xbd223d46,
0x3d6dbcc4,0xbd223d46,0x3c48bd7b,0x3c953d75,0x80003d80,0xbcf1bd62,0x3d553d0e,0xbd7fbbc9,0xbcc43d6d,0xbbc9bd7f,0x3d0e3d55,0xbd62bcf1,0xbd35bd35,0x3d753c95,0xbd7b3c48,0x3d46bd22,
0x3cc43d6d,0xbd46bd22,0x3d7b3c48,0xbd753c95,0xbd800000,0x3d62bcf1,0xbd0e3d55,0x3bc9bd7f,0xbd6dbcc4,0x3d7fbbc9,0xbd553d0e,0x3cf1bd62,0x3d35bd35,0xbc953d75,0xbc48bd7b,0x3d223d46,
0xbd353d35,0x3cf1bd62,0xbc483d7b,0xbbc9bd7f,0x3cc43d6d,0xbd22bd46,0x3d553d0e,0xbd75bc95,0x8000bd80,0x3c953d75,0xbd0ebd55,0x3d463d22,0xbd6dbcc4,0x3d7f3bc9,0xbd7b3c48,0x3d62bcf1,
0x3d353d35,0xbd62bcf1,0x3d7b3c48,0xbd7f3bc9,0x3d6dbcc4,0xbd463d22,0x3d0ebd55,0xbc953d75,0xbd800000,0x3d75bc95,0xbd553d0e,0x3d22bd46,0xbcc43d6d,0x3bc9bd7f,0x3c483d7b,0xbcf1bd62,
0x3d6d3cc4,0xbd75bc95,0x3d7b3c48,0xbd7fbbc9,0x3d353d35,0xbd46bd22,0x3d553d0e,0xbd62bcf1,0x3cc43d6d,0xbcf1bd62,0x3d0e3d55,0xbd22bd46,0x80003d80,0xbbc9bd7f,0x3c483d7b,0xbc95bd75,
0xbcc43d6d,0x3c95bd75,0xbc483d7b,0x3bc9bd7f,0xbd353d35,0x3d22bd46,0xbd0e3d55,0x3cf1bd62,0xbd6d3cc4,0x3d62bcf1,0xbd553d0e,0x3d46bd22,0xbd800000,0x3d7fbbc9,0xbd7b3c48,0x3d75bc95,
0x3d80,0x3bc9bd7f,0xbc483d7b,0x3c95bd75,0xbcc43d6d,0x3cf1bd62,0xbd0e3d55,0x3d22bd46,0xbd353d35,0x3d46bd22,0xbd553d0e,0x3d62bcf1,0xbd6d3cc4,0x3d75bc95,0xbd7b3c48,0x3d7fbbc9,
0xbd800000,0x3d7f3bc9,0xbd7bbc48,0x3d753c95,0xbd6dbcc4,0x3d623cf1,0xbd55bd0e,0x3d463d22,0xbd35bd35,0x3d223d46,0xbd0ebd55,0x3cf13d62,0xbcc4bd6d,0x3c953d75,0xbc48bd7b,0x3bc93d7f,
0xbd6d3cc4,0x3d7fbbc9,0xbd7bbc48,0x3d623cf1,0x3d80,0x3c95bd75,0xbd0e3d55,0x3d46bd22,0x3cc4bd6d,0xbd223d46,0x3d55bd0e,0xbd753c95,0xbd35bd35,0x3cf13d62,0xbc48bd7b,0xbbc93d7f,
0x3cc43d6d,0xbbc9bd7f,0xbc483d7b,0x3cf1bd62,0x3d800000,0xbd75bc95,0x3d553d0e,0xbd22bd46,0xbd6dbcc4,0x3d463d22,0xbd0ebd55,0x3c953d75,0xbd353d35,0x3d62bcf1,0xbd7b3c48,0x3d7f3bc9,
0x3d35bd35,0xbd753c95,0x3d7b3c48,0xbd46bd22,0x3cc43d6d,0x3bc9bd7f,0xbd0e3d55,0x3d62bcf1,0x3d80,0x3cf1bd62,0xbd553d0e,0x3d7fbbc9,0xbd6dbcc4,0x3d223d46,0xbc48bd7b,0xbc953d75,
0x3d353d35,0xbc95bd75,0xbc483d7b,0x3d22bd46,0xbd6d3cc4,0x3d7f3bc9,0xbd55bd0e,0x3cf13d62,0xbd800000,0x3d623cf1,0xbd0ebd55,0x3bc93d7f,0x3cc4bd6d,0xbd463d22,0x3d7bbc48,0xbd75bc95,
0xbd6dbcc4,0x3cf13d62,0x3c48bd7b,0xbd463d22,0x3d353d35,0xbbc9bd7f,0xbd0e3d55,0x3d75bc95,0xbcc4bd6d,0xbc953d75,0x3d55bd0e,0xbd7fbbc9,0x3d80,0x3d22bd46,0xbd7b3c48,0x3d623cf1,
0xbcc43d6d,0x3d62bcf1,0xbd7bbc48,0x3d223d46,0x3d35bd35,0xbd7f3bc9,0x3d553d0e,0xbc95bd75,0xbd6d3cc4,0x3d753c95,0xbd0ebd55,0xbbc93d7f,0x3d800000,0xbd46bd22,0x3c483d7b,0x3cf1bd62,
0xbd800000,0x3d223d46,0x3c48bd7b,0xbd623cf1,0x3d6d3cc4,0xbc95bd75,0xbd0e3d55,0x3d7fbbc9,0xbd35bd35,0xbbc93d7f,0x3d55bd0e,0xbd75bc95,0x3cc43d6d,0x3cf1bd62,0xbd7b3c48,0x3d463d22,
0x3d80,0x3d46bd22,0xbd7bbc48,0x3cf13d62,0x3cc4bd6d,0xbd753c95,0x3d553d0e,0xbbc9bd7f,0xbd353d35,0x3d7f3bc9,0xbd0ebd55,0xbc953d75,0x3d6dbcc4,0xbd62bcf1,0x3c483d7b,0x3d22bd46,
0xbcc4bd6d,0xbd223d46,0x3d7b3c48,0xbc95bd75,0x3d800000,0xbcf1bd62,0xbd0e3d55,0x3d7f3bc9,0x3d6d3cc4,0xbbc9bd7f,0xbd553d0e,0x3d623cf1,0xbd353d35,0x3d753c95,0xbc48bd7b,0xbd463d22,
0x3d6dbcc4,0xbd46bd22,0xbc483d7b,0x3d75bc95,0x3d80,0x3d62bcf1,0xbd55bd0e,0xbbc93d7f,0xbcc43d6d,0x3d7fbbc9,0xbd0ebd55,0xbcf13d62,0xbd35bd35,0xbc953d75,0x3d7bbc48,0xbd22bd46,
0x3d353d35,0x3cf1bd62,0xbd7bbc48,0x3bc93d7f,0x3d6dbcc4,0xbd22bd46,0xbd0e3d55,0x3d753c95,0xbd800000,0x3c953d75,0x3d55bd0e,0xbd46bd22,0xbcc43d6d,0x3d7f3bc9,0xbc48bd7b,0xbd623cf1,
0x3d35bd35,0xbd62bcf1,0xbc483d7b,0x3d7fbbc9,0xbcc4bd6d,0xbd463d22,0x3d553d0e,0x3c95bd75,0x3d80,0x3d75bc95,0xbd0ebd55,0xbd223d46,0x3d6d3cc4,0x3bc9bd7f,0xbd7b3c48,0x3cf13d62,
0x3cc4bd6d,0xbd75bc95,0xbc483d7b,0x3d7f3bc9,0x3d35bd35,0xbd46bd22,0xbd0e3d55,0x3d623cf1,0x3d6dbcc4,0xbcf1bd62,0xbd553d0e,0x3d223d46,0x3d800000,0xbbc9bd7f,0xbd7b3c48,0x3c953d75,
0x3d6d3cc4,0x3c95bd75,0xbd7bbc48,0xbbc93d7f,0x3d353d35,0x3d22bd46,0xbd55bd0e,0xbcf13d62,0x3cc43d6d,0x3d62bcf1,0xbd0ebd55,0xbd463d22,0x3d80,0x3d7fbbc9,0xbc48bd7b,0xbd753c95,
0xbd800000,0x3d7f3bc9,0xbd7bbc48,0x3d753c95,0xbd6dbcc4,0x3d623cf1,0xbd55bd0e,0x3d463d22,0xbd35bd35,0x3d223d46,0xbd0ebd55,0x3cf13d62,0xbcc4bd6d,0x3c953d75,0xbc48bd7b,0x3bc93d7f,
0x8000bd80,0xbbc93d7f,0x3c48bd7b,0xbc953d75,0x3cc4bd6d,0xbcf13d62,0x3d0ebd55,0xbd223d46,0x3d35bd35,0xbd463d22,0x3d55bd0e,0xbd623cf1,0x3d6dbcc4,0xbd753c95,0x3d7bbc48,0xbd7f3bc9,
0xbcc4bd6d,0x3bc93d7f,0x3c48bd7b,0xbcf13d62,0xbd800000,0x3d753c95,0xbd55bd0e,0x3d223d46,0x3d6d3cc4,0xbd46bd22,0x3d0e3d55,0xbc95bd75,0x3d35bd35,0xbd623cf1,0x3d7bbc48,0xbd7fbbc9,
0xbd6d3cc4,0x3d7fbbc9,0xbd7bbc48,0x3d623cf1,0x80003d80,0x3c95bd75,0xbd0e3d55,0x3d46bd22,0x3cc4bd6d,0xbd223d46,0x3d55bd0e,0xbd753c95,0xbd35bd35,0x3cf13d62,0xbc48bd7b,0xbbc93d7f,
0x3d353d35,0xbc95bd75,0xbc483d7b,0x3d22bd46,0xbd6d3cc4,0x3d7f3bc9,0xbd55bd0e,0x3cf13d62,0xbd800000,0x3d623cf1,0xbd0ebd55,0x3bc93d7f,0x3cc4bd6d,0xbd463d22,0x3d7bbc48,0xbd75bc95,
0xbd353d35,0x3d75bc95,0xbd7bbc48,0x3d463d22,0xbcc4bd6d,0xbbc93d7f,0x3d0ebd55,0xbd623cf1,0x8000bd80,0xbcf13d62,0x3d55bd0e,0xbd7f3bc9,0x3d6d3cc4,0xbd22bd46,0x3c483d7b,0x3c95bd75,
0x3cc4bd6d,0xbd623cf1,0x3d7b3c48,0xbd22bd46,0xbd353d35,0x3d7fbbc9,0xbd55bd0e,0x3c953d75,0x3d6dbcc4,0xbd75bc95,0x3d0e3d55,0x3bc9bd7f,0xbd800000,0x3d463d22,0xbc48bd7b,0xbcf13d62,
0xbd6dbcc4,0x3cf13d62,0x3c48bd7b,0xbd463d22,0x3d353d35,0xbbc9bd7f,0xbd0e3d55,0x3d75bc95,0xbcc4bd6d,0xbc953d75,0x3d55bd0e,0xbd7fbbc9,0x80003d80,0x3d22bd46,0xbd7b3c48,0x3d623cf1,
0x8000bd80,0xbd463d22,0x3d7b3c48,0xbcf1bd62,0xbcc43d6d,0x3d75bc95,0xbd55bd0e,0x3bc93d7f,0x3d35bd35,0xbd7fbbc9,0x3d0e3d55,0x3c95bd75,0xbd6d3cc4,0x3d623cf1,0xbc48bd7b,0xbd223d46,
0xbd800000,0x3d223d46,0x3c48bd7b,0xbd623cf1,0x3d6d3cc4,0xbc95bd75,0xbd0e3d55,0x3d7fbbc9,0xbd35bd35,0xbbc93d7f,0x3d55bd0e,0xbd75bc95,0x3cc43d6d,0x3cf1bd62,0xbd7b3c48,0x3d463d22,
0x3d6dbcc4,0xbd46bd22,0xbc483d7b,0x3d75bc95,0x80003d80,0x3d62bcf1,0xbd55bd0e,0xbbc93d7f,0xbcc43d6d,0x3d7fbbc9,0xbd0ebd55,0xbcf13d62,0xbd35bd35,0xbc953d75,0x3d7bbc48,0xbd22bd46,
0x3cc43d6d,0x3d22bd46,0xbd7bbc48,0x3c953d75,0xbd800000,0x3cf13d62,0x3d0ebd55,0xbd7fbbc9,0xbd6dbcc4,0x3bc93d7f,0x3d55bd0e,0xbd62bcf1,0x3d35bd35,0xbd75bc95,0x3c483d7b,0x3d46bd22,
0xbd353d35,0x3d623cf1,0x3c48bd7b,0xbd7f3bc9,0x3cc43d6d,0x3d46bd22,0xbd55bd0e,0xbc953d75,0x8000bd80,0xbd753c95,0x3d0e3d55,0x3d22bd46,0xbd6dbcc4,0xbbc93d7f,0x3d7bbc48,0xbcf1bd62,
0x3d353d35,0x3cf1bd62,0xbd7bbc48,0x3bc93d7f,0x3d6dbcc4,0xbd22bd46,0xbd0e3d55,0x3d753c95,0xbd800000,0x3c953d75,0x3d55bd0e,0xbd46bd22,0xbcc43d6d,0x3d7f3bc9,0xbc48bd7b,0xbd623cf1,
0x3d6d3cc4,0x3c95bd75,0xbd7bbc48,0xbbc93d7f,0x3d353d35,0x3d22bd46,0xbd55bd0e,0xbcf13d62,0x3cc43d6d,0x3d62bcf1,0xbd0ebd55,0xbd463d22,0x80003d80,0x3d7fbbc9,0xbc48bd7b,0xbd753c95,
0xbcc43d6d,0x3d753c95,0x3c48bd7b,0xbd7fbbc9,0xbd353d35,0x3d463d22,0x3d0ebd55,0xbd62bcf1,0xbd6d3cc4,0x3cf13d62,0x3d55bd0e,0xbd22bd46,0xbd800000,0x3bc93d7f,0x3d7bbc48,0xbc95bd75,
0x3d80,0x3d7f3bc9,0x3c48bd7b,0xbd75bc95,0xbcc43d6d,0x3d623cf1,0x3d0ebd55,0xbd46bd22,0xbd353d35,0x3d223d46,0x3d55bd0e,0xbcf1bd62,0xbd6d3cc4,0x3c953d75,0x3d7bbc48,0xbbc9bd7f,
0xbd800000,0xbbc93d7f,0x3d7b3c48,0x3c95bd75,0xbd6dbcc4,0xbcf13d62,0x3d553d0e,0x3d22bd46,0xbd35bd35,0xbd463d22,0x3d0e3d55,0x3d62bcf1,0xbcc4bd6d,0xbd753c95,0x3c483d7b,0x3d7fbbc9,
0xbd6d3cc4,0x3bc93d7f,0x3d7b3c48,0x3cf1bd62,0x3d80,0x3d753c95,0x3d0ebd55,0xbd22bd46,0x3cc4bd6d,0xbd46bd22,0xbd553d0e,0x3c953d75,0xbd35bd35,0xbd623cf1,0x3c483d7b,0x3d7f3bc9,
0x3cc43d6d,0x3d7fbbc9,0x3c48bd7b,0xbd62bcf1,0x3d800000,0x3c95bd75,0xbd55bd0e,0xbd463d22,0xbd6dbcc4,0xbd223d46,0x3d0e3d55,0x3d75bc95,0xbd353d35,0x3cf13d62,0x3d7bbc48,0x3bc9bd7f,
0x3d35bd35,0xbc95bd75,0xbd7bbc48,0xbd223d46,0x3cc43d6d,0x3d7f3bc9,0x3d0ebd55,0xbcf1bd62,0x3d80,0x3d623cf1,0x3d55bd0e,0xbbc9bd7f,0xbd6dbcc4,0xbd463d22,0x3c483d7b,0x3d753c95,
0x3d353d35,0x3d75bc95,0x3c48bd7b,0xbd46bd22,0xbd6d3cc4,0xbbc93d7f,0x3d553d0e,0x3d62bcf1,0xbd800000,0xbcf13d62,0x3d0e3d55,0x3d7fbbc9,0x3cc4bd6d,0xbd22bd46,0xbd7b3c48,0xbc953d75,
0xbd6dbcc4,0xbd623cf1,0xbc483d7b,0x3d223d46,0x3d353d35,0x3d7fbbc9,0x3d0ebd55,0xbc95bd75,0xbcc4bd6d,0xbd75bc95,0xbd553d0e,0xbbc93d7f,0x3d80,0x3d463d22,0x3d7bbc48,0x3cf1bd62,
0xbcc43d6d,0x3cf13d62,0x3d7b3c48,0x3d46bd22,0x3d35bd35,0xbbc9bd7f,0xbd55bd0e,0xbd753c95,0xbd6d3cc4,0xbc953d75,0x3d0e3d55,0x3d7f3bc9,0x3d800000,0x3d22bd46,0xbc48bd7b,0xbd62bcf1,
0xbd800000,0xbd463d22,0xbc483d7b,0x3cf13d62,0x3d6d3cc4,0x3d75bc95,0x3d0ebd55,0xbbc9bd7f,0xbd35bd35,0xbd7fbbc9,0xbd553d0e,0xbc953d75,0x3cc43d6d,0x3d623cf1,0x3d7bbc48,0x3d22bd46,
0x3d80,0x3d223d46,0x3d7b3c48,0x3d62bcf1,0x3cc4bd6d,0xbc95bd75,0xbd55bd0e,0xbd7f3bc9,0xbd353d35,0xbbc93d7f,0x3d0e3d55,0x3d753c95,0x3d6dbcc4,0x3cf1bd62,0xbc48bd7b,0xbd46bd22,
0xbcc4bd6d,0xbd46bd22,0xbd7bbc48,0xbd753c95,0x3d800000,0x3d62bcf1,0x3d0ebd55,0x3bc9bd7f,0x3d6d3cc4,0x3d7fbbc9,0x3d55bd0e,0x3cf1bd62,0xbd353d35,0xbc953d75,0x3c483d7b,0x3d223d46,
0x3d6dbcc4,0x3d22bd46,0x3c48bd7b,0xbc95bd75,0x3d80,0x3cf13d62,0x3d553d0e,0x3d7f3bc9,0xbcc43d6d,0x3bc93d7f,0x3d0e3d55,0x3d623cf1,0xbd35bd35,0xbd75bc95,0xbd7b3c48,0xbd463d22,
0x3d353d35,0x3d623cf1,0x3d7b3c48,0x3d7fbbc9,0x3d6dbcc4,0x3d46bd22,0x3d0ebd55,0x3c95bd75,0xbd800000,0xbd753c95,0xbd553d0e,0xbd223d46,0xbcc43d6d,0xbbc93d7f,0x3c483d7b,0x3cf13d62,
0x3d35bd35,0x3cf1bd62,0x3c48bd7b,0xbbc9bd7f,0xbcc4bd6d,0xbd22bd46,0xbd55bd0e,0xbd75bc95,0x3d80,0x3c953d75,0x3d0e3d55,0x3d463d22,0x3d6d3cc4,0x3d7f3bc9,0x3d7bbc48,0x3d62bcf1,
0x3cc4bd6d,0x3c95bd75,0x3c48bd7b,0x3bc9bd7f,0x3d35bd35,0x3d22bd46,0x3d0ebd55,0x3cf1bd62,0x3d6dbcc4,0x3d62bcf1,0x3d55bd0e,0x3d46bd22,0x3d800000,0x3d7fbbc9,0x3d7bbc48,0x3d75bc95,
0x3d6d3cc4,0x3d753c95,0x3d7b3c48,0x3d7f3bc9,0x3d353d35,0x3d463d22,0x3d553d0e,0x3d623cf1,0x3cc43d6d,0x3cf13d62,0x3d0e3d55,0x3d223d46,0x3d80,0x3bc93d7f,0x3c483d7b,0x3c953d75,
0xbd800000,0xbbc93d7f,0x3d7b3c48,0x3c95bd75,0xbd6dbcc4,0xbcf13d62,0x3d553d0e,0x3d22bd46,0xbd35bd35,0xbd463d22,0x3d0e3d55,0x3d62bcf1,0xbcc4bd6d,0xbd753c95,0x3c483d7b,0x3d7fbbc9,
0x8000bd80,0xbd7fbbc9,0xbc483d7b,0x3d753c95,0x3cc4bd6d,0xbd62bcf1,0xbd0e3d55,0x3d463d22,0x3d35bd35,0xbd22bd46,0xbd553d0e,0x3cf13d62,0x3d6dbcc4,0xbc95bd75,0xbd7b3c48,0x3bc93d7f,
0xbcc4bd6d,0xbd7f3bc9,0xbc483d7b,0x3d623cf1,0xbd800000,0xbc953d75,0x3d553d0e,0x3d46bd22,0x3d6d3cc4,0x3d22bd46,0xbd0ebd55,0xbd753c95,0x3d35bd35,0xbcf1bd62,0xbd7b3c48,0xbbc93d7f,
0xbd6d3cc4,0x3bc93d7f,0x3d7b3c48,0x3cf1bd62,0x80003d80,0x3d753c95,0x3d0ebd55,0xbd22bd46,0x3cc4bd6d,0xbd46bd22,0xbd553d0e,0x3c953d75,0xbd35bd35,0xbd623cf1,0x3c483d7b,0x3d7f3bc9,
0x3d353d35,0x3d75bc95,0x3c48bd7b,0xbd46bd22,0xbd6d3cc4,0xbbc93d7f,0x3d553d0e,0x3d62bcf1,0xbd800000,0xbcf13d62,0x3d0e3d55,0x3d7fbbc9,0x3cc4bd6d,0xbd22bd46,0xbd7b3c48,0xbc953d75,
0xbd353d35,0x3c953d75,0x3d7b3c48,0x3d22bd46,0xbcc4bd6d,0xbd7fbbc9,0xbd0e3d55,0x3cf13d62,0x8000bd80,0xbd62bcf1,0xbd553d0e,0x3bc93d7f,0x3d6d3cc4,0x3d46bd22,0xbc48bd7b,0xbd75bc95,
0x3cc4bd6d,0xbcf1bd62,0xbd7bbc48,0xbd463d22,0xbd353d35,0x3bc93d7f,0x3d553d0e,0x3d75bc95,0x3d6dbcc4,0x3c95bd75,0xbd0ebd55,0xbd7fbbc9,0xbd800000,0xbd223d46,0x3c483d7b,0x3d623cf1,
0xbd6dbcc4,0xbd623cf1,0xbc483d7b,0x3d223d46,0x3d353d35,0x3d7fbbc9,0x3d0ebd55,0xbc95bd75,0xbcc4bd6d,0xbd75bc95,0xbd553d0e,0xbbc93d7f,0x80003d80,0x3d463d22,0x3d7bbc48,0x3cf1bd62,
0x8000bd80,0xbd22bd46,0xbd7bbc48,0xbd623cf1,0xbcc43d6d,0x3c953d75,0x3d553d0e,0x3d7fbbc9,0x3d35bd35,0x3bc9bd7f,0xbd0ebd55,0xbd75bc95,0xbd6d3cc4,0xbcf13d62,0x3c483d7b,0x3d463d22,
0xbd800000,0xbd463d22,0xbc483d7b,0x3cf13d62,0x3d6d3cc4,0x3d75bc95,0x3d0ebd55,0xbbc9bd7f,0xbd35bd35,0xbd7fbbc9,0xbd553d0e,0xbc953d75,0x3cc43d6d,0x3d623cf1,0x3d7bbc48,0x3d22bd46,
0x3d6dbcc4,0x3d22bd46,0x3c48bd7b,0xbc95bd75,0x80003d80,0x3cf13d62,0x3d553d0e,0x3d7f3bc9,0xbcc43d6d,0x3bc93d7f,0x3d0e3d55,0x3d623cf1,0xbd35bd35,0xbd75bc95,0xbd7b3c48,0xbd463d22,
0x3cc43d6d,0x3d463d22,0x3d7b3c48,0x3d75bc95,0xbd800000,0xbd623cf1,0xbd0e3d55,0xbbc93d7f,0xbd6dbcc4,0xbd7f3bc9,0xbd553d0e,0xbcf13d62,0x3d35bd35,0x3c95bd75,0xbc48bd7b,0xbd22bd46,
0xbd353d35,0xbcf13d62,0xbc483d7b,0x3bc93d7f,0x3cc43d6d,0x3d223d46,0x3d553d0e,0x3d753c95,0x8000bd80,0xbc95bd75,0xbd0ebd55,0xbd46bd22,0xbd6dbcc4,0xbd7fbbc9,0xbd7b3c48,0xbd623cf1,
0x3d353d35,0x3d623cf1,0x3d7b3c48,0x3d7fbbc9,0x3d6dbcc4,0x3d46bd22,0x3d0ebd55,0x3c95bd75,0xbd800000,0xbd753c95,0xbd553d0e,0xbd223d46,0xbcc43d6d,0xbbc93d7f,0x3c483d7b,0x3cf13d62,
0x3d6d3cc4,0x3d753c95,0x3d7b3c48,0x3d7f3bc9,0x3d353d35,0x3d463d22,0x3d553d0e,0x3d623cf1,0x3cc43d6d,0x3cf13d62,0x3d0e3d55,0x3d223d46,0x80003d80,0x3bc93d7f,0x3c483d7b,0x3c953d75,
0xbcc43d6d,0xbc953d75,0xbc483d7b,0xbbc93d7f,0xbd353d35,0xbd223d46,0xbd0e3d55,0xbcf13d62,0xbd6d3cc4,0xbd623cf1,0xbd553d0e,0xbd463d22,0xbd800000,0xbd7f3bc9,0xbd7b3c48,0xbd753c95,
0x3d80,0xbc163d7d,0xbc953d75,0xbcdb3d67,0xbd0e3d55,0xbd2c3d3e,0xbd463d22,0xbd5c3d04,0xbd6d3cc4,0xbd783c79,0xbd7f3bc9,0xbd80bb49,0xbd7bbc48,0xbd71bcac,0xbd62bcf1,0xbd4ebd18,
0xbd35bd35,0xbd18bd4e,0xbcf1bd62,0xbcacbd71,0xbc48bd7b,0xbb49bd80,0x3bc9bd7f,0x3c79bd78,0x3cc4bd6d,0x3d04bd5c,0x3d22bd46,0x3d3ebd2c,0x3d55bd0e,0x3d67bcdb,0x3d75bc95,0x3d7dbc16,
0xbd7b3c48,0xbd7dbc16,0xbd62bcf1,0xbd2cbd3e,0x3d80,0xbcac3d71,0xbd223d46,0xbd5c3d04,0x3d55bd0e,0x3d78bc79,0x3d7f3bc9,0x3d673cdb,0xbcc4bd6d,0xbb49bd80,0x3c95bd75,0x3d18bd4e,
0xbd0e3d55,0xbd4e3d18,0xbd753c95,0xbd80bb49,0x3d353d35,0x3cdb3d67,0x3bc93d7f,0xbc793d78,0x3c48bd7b,0x3d04bd5c,0x3d46bd22,0x3d71bcac,0xbd6dbcc4,0xbd3ebd2c,0xbcf1bd62,0xbc16bd7d,
0x3d6dbcc4,0x3d7d3c16,0x3d463d22,0x3cac3d71,0xbc483d7b,0xbd2c3d3e,0xbd753c95,0xbd78bc79,0x3d80,0xbd043d5c,0xbd623cf1,0xbd80bb49,0xbd55bd0e,0xbcdbbd67,0x3bc9bd7f,0x3d18bd4e,
0xbcc43d6d,0xbd4e3d18,0xbd7f3bc9,0xbd67bcdb,0xbd0ebd55,0xbb49bd80,0x3cf1bd62,0x3d5cbd04,0xbd35bd35,0xbc79bd78,0x3c95bd75,0x3d3ebd2c,0x3d7bbc48,0x3d713cac,0x3d223d46,0x3c163d7d,
0xbd0ebd55,0x3c16bd7d,0x3d46bd22,0x3d803b49,0x3cc43d6d,0xbcac3d71,0xbd623cf1,0xbd78bc79,0xbc48bd7b,0x3d04bd5c,0x3d75bc95,0x3d673cdb,0x3d80,0xbd2c3d3e,0xbd7f3bc9,0xbd4ebd18,
0xbd7bbc48,0xbd18bd4e,0x3bc9bd7f,0x3d3ebd2c,0x3d6d3cc4,0x3cdb3d67,0xbc953d75,0xbd5c3d04,0xbd55bd0e,0xbc79bd78,0x3cf1bd62,0x3d71bcac,0x3d353d35,0x3b493d80,0xbd223d46,0xbd7d3c16,
0xbd35bd35,0x3c16bd7d,0x3d62bcf1,0x3d673cdb,0x3c483d7b,0xbd2c3d3e,0xbd7fbbc9,0xbd04bd5c,0x3cc4bd6d,0x3d78bc79,0x3d463d22,0xbb493d80,0xbd553d0e,0xbd71bcac,0xbc95bd75,0x3d18bd4e,
0x3d80,0xbd4e3d18,0xbd75bc95,0xbcacbd71,0x3d0ebd55,0x3d80bb49,0x3d223d46,0xbc793d78,0xbd6d3cc4,0xbd5cbd04,0xbbc9bd7f,0x3d3ebd2c,0x3d7b3c48,0x3cdb3d67,0xbcf13d62,0xbd7d3c16,
0x3d0ebd55,0x3d7d3c16,0x3c953d75,0xbd3e3d2c,0x3d353d35,0xbcac3d71,0xbd7f3bc9,0xbd04bd5c,0xbc483d7b,0xbd783c79,0xbd22bd46,0x3cdbbd67,0xbd6dbcc4,0xbb49bd80,0x3d62bcf1,0x3d4e3d18,
0x3d7bbc48,0x3d183d4e,0xbcf13d62,0xbd80bb49,0x3d80,0xbd673cdb,0xbd46bd22,0x3c79bd78,0xbd553d0e,0xbd5cbd04,0x3bc9bd7f,0x3d71bcac,0xbcc4bd6d,0x3d2cbd3e,0x3d753c95,0x3c163d7d,
0xbcc43d6d,0xbd7dbc16,0xbbc9bd7f,0x3d71bcac,0x3d0e3d55,0xbd2c3d3e,0xbd62bcf1,0x3c79bd78,0xbd35bd35,0x3d04bd5c,0x3d753c95,0xbb493d80,0xbd7b3c48,0xbcdbbd67,0x3d46bd22,0x3d4e3d18,
0x3d6dbcc4,0x3d183d4e,0xbd223d46,0xbd67bcdb,0x3c48bd7b,0x3d80bb49,0x3c953d75,0xbd5c3d04,0x3d80,0xbd783c79,0xbcf1bd62,0x3d3ebd2c,0x3d553d0e,0xbcac3d71,0xbd7fbbc9,0xbc16bd7d,
0x3d7b3c48,0xbc163d7d,0xbd7fbbc9,0x3b49bd80,0x3d6d3cc4,0xbcac3d71,0xbd75bc95,0x3c79bd78,0x3d553d0e,0xbd043d5c,0xbd62bcf1,0x3cdbbd67,0x3d353d35,0xbd2c3d3e,0xbd46bd22,0x3d18bd4e,
0x3d0e3d55,0xbd4e3d18,0xbd22bd46,0x3d3ebd2c,0x3cc43d6d,0xbd673cdb,0xbcf1bd62,0x3d5cbd04,0x3c483d7b,0xbd783c79,0xbc95bd75,0x3d71bcac,0x3d80,0xbd803b49,0xbbc9bd7f,0x3d7dbc16,
0xbd800000,0xbd7dbc16,0xbd75bc95,0xbd67bcdb,0xbd55bd0e,0xbd3ebd2c,0xbd22bd46,0xbd04bd5c,0xbcc4bd6d,0xbc79bd78,0xbbc9bd7f,0x3b49bd80,0x3c48bd7b,0x3cacbd71,0x3cf1bd62,0x3d18bd4e,
0x3d35bd35,0x3d4ebd18,0x3d62bcf1,0x3d71bcac,0x3d7bbc48,0x3d80bb49,0x3d7f3bc9,0x3d783c79,0x3d6d3cc4,0x3d5c3d04,0x3d463d22,0x3d2c3d3e,0x3d0e3d55,0x3cdb3d67,0x3c953d75,0x3c163d7d,
0xbc48bd7b,0x3c16bd7d,0x3cf1bd62,0x3d3ebd2c,0xbd800000,0xbd71bcac,0xbd46bd22,0xbd04bd5c,0x3d0e3d55,0x3c793d78,0xbbc93d7f,0xbcdb3d67,0x3d6dbcc4,0x3d80bb49,0x3d753c95,0x3d4e3d18,
0xbd55bd0e,0xbd18bd4e,0xbc95bd75,0x3b49bd80,0xbd353d35,0xbd673cdb,0xbd7f3bc9,0xbd78bc79,0x3d7b3c48,0x3d5c3d04,0x3d223d46,0x3cac3d71,0x3cc4bd6d,0x3d2cbd3e,0x3d62bcf1,0x3d7dbc16,
0x3cc43d6d,0xbc163d7d,0xbd223d46,0xbd713cac,0xbd7bbc48,0xbd3ebd2c,0xbc95bd75,0x3c79bd78,0xbd800000,0xbd5cbd04,0xbcf1bd62,0x3b49bd80,0x3d0ebd55,0x3d67bcdb,0x3d7f3bc9,0x3d4e3d18,
0xbd6dbcc4,0xbd18bd4e,0xbbc9bd7f,0x3cdbbd67,0x3d55bd0e,0x3d80bb49,0x3d623cf1,0x3d043d5c,0x3d35bd35,0x3d78bc79,0x3d753c95,0x3d2c3d3e,0x3c483d7b,0xbcac3d71,0xbd463d22,0xbd7d3c16,
0x3d55bd0e,0x3d7d3c16,0x3d223d46,0xbb493d80,0xbd6d3cc4,0xbd71bcac,0xbcf1bd62,0x3c79bd78,0x3d7bbc48,0x3d5c3d04,0x3c953d75,0xbcdb3d67,0xbd800000,0xbd3ebd2c,0xbbc9bd7f,0x3d18bd4e,
0x3c48bd7b,0x3d4ebd18,0x3d7f3bc9,0x3d2c3d3e,0xbcc43d6d,0xbd673cdb,0xbd75bc95,0xbd04bd5c,0x3d0ebd55,0x3d78bc79,0x3d623cf1,0x3cac3d71,0xbd353d35,0xbd803b49,0xbd46bd22,0xbc16bd7d,
0x3d35bd35,0x3d7d3c16,0x3cf13d62,0xbcdb3d67,0xbd7b3c48,0xbd3ebd2c,0x3bc9bd7f,0x3d5cbd04,0x3d6d3cc4,0x3c793d78,0xbd223d46,0xbd80bb49,0xbd0ebd55,0x3cacbd71,0x3d75bc95,0x3d4e3d18,
0xbd800000,0xbd18bd4e,0x3c95bd75,0x3d71bcac,0x3d553d0e,0x3b493d80,0xbd463d22,0xbd78bc79,0xbcc4bd6d,0x3d04bd5c,0x3d7fbbc9,0x3d2c3d3e,0xbc483d7b,0xbd673cdb,0xbd62bcf1,0xbc16bd7d,
0x3d553d0e,0xbc163d7d,0xbd753c95,0xbd2cbd3e,0xbd353d35,0xbd71bcac,0xbbc9bd7f,0x3d5cbd04,0xbd7bbc48,0xbc79bd78,0x3d46bd22,0x3d673cdb,0x3cc4bd6d,0x3d80bb49,0x3cf13d62,0xbd183d4e,
0x3c483d7b,0xbd4e3d18,0xbd62bcf1,0x3b49bd80,0xbd800000,0xbcdbbd67,0x3d22bd46,0x3d783c79,0xbd0ebd55,0x3d04bd5c,0x3d7f3bc9,0x3cac3d71,0x3d6dbcc4,0x3d3e3d2c,0xbc953d75,0xbd7d3c16,
0xbd6dbcc4,0x3c16bd7d,0x3d7fbbc9,0x3cac3d71,0xbd553d0e,0xbd3ebd2c,0x3cf1bd62,0x3d783c79,0x3d35bd35,0x3d5c3d04,0xbc953d75,0xbd80bb49,0xbc48bd7b,0x3d67bcdb,0x3d223d46,0xbd183d4e,
0x3cc43d6d,0xbd4e3d18,0xbd46bd22,0x3cdbbd67,0x3d7b3c48,0x3b493d80,0xbd753c95,0xbd04bd5c,0xbd800000,0xbc79bd78,0x3d62bcf1,0x3d2c3d3e,0xbd0e3d55,0xbd71bcac,0x3bc9bd7f,0x3d7dbc16,
0xbc483d7b,0xbd7dbc16,0x3bc9bd7f,0x3d803b49,0xbcc43d6d,0xbd71bcac,0x3c95bd75,0x3d783c79,0xbd0e3d55,0xbd5cbd04,0x3cf1bd62,0x3d673cdb,0xbd353d35,0xbd3ebd2c,0x3d22bd46,0x3d4e3d18,
0xbd553d0e,0xbd18bd4e,0x3d46bd22,0x3d2c3d3e,0xbd6d3cc4,0xbcdbbd67,0x3d62bcf1,0x3d043d5c,0xbd7b3c48,0xbc79bd78,0x3d75bc95,0x3cac3d71,0xbd800000,0xbb49bd80,0x3d7fbbc9,0x3c163d7d,
0x3d80,0xbd7dbc16,0x3c95bd75,0x3d673cdb,0xbd0e3d55,0xbd3ebd2c,0x3d46bd22,0x3d043d5c,0xbd6d3cc4,0xbc79bd78,0x3d7fbbc9,0xbb493d80,0xbd7bbc48,0x3cacbd71,0x3d623cf1,0xbd183d4e,
0xbd35bd35,0x3d4ebd18,0x3cf13d62,0xbd713cac,0xbc48bd7b,0x3d80bb49,0xbbc93d7f,0xbd78bc79,0x3cc4bd6d,0x3d5c3d04,0xbd223d46,0xbd2cbd3e,0x3d55bd0e,0x3cdb3d67,0xbd753c95,0xbc16bd7d,
0xbd7b3c48,0x3c16bd7d,0x3d623cf1,0xbd3e3d2c,0x3d80,0xbd71bcac,0x3d22bd46,0x3d043d5c,0x3d55bd0e,0x3c793d78,0xbd7fbbc9,0x3cdbbd67,0xbcc4bd6d,0x3d80bb49,0xbc953d75,0xbd4ebd18,
0xbd0e3d55,0xbd18bd4e,0x3d75bc95,0xbb493d80,0x3d353d35,0xbd673cdb,0xbbc9bd7f,0x3d783c79,0x3c48bd7b,0x3d5c3d04,0xbd463d22,0xbcacbd71,0xbd6dbcc4,0x3d2cbd3e,0x3cf13d62,0xbd7d3c16,
0x3d6dbcc4,0xbc163d7d,0xbd46bd22,0x3d71bcac,0xbc483d7b,0xbd3ebd2c,0x3d75bc95,0xbc793d78,0x3d80,0xbd5cbd04,0x3d62bcf1,0xbb493d80,0xbd55bd0e,0x3d67bcdb,0xbbc93d7f,0xbd4ebd18,
0xbcc43d6d,0xbd18bd4e,0x3d7fbbc9,0xbcdb3d67,0xbd0ebd55,0x3d80bb49,0xbcf13d62,0xbd04bd5c,0xbd35bd35,0x3d78bc79,0xbc953d75,0xbd2cbd3e,0x3d7bbc48,0xbcac3d71,0xbd22bd46,0x3d7dbc16,
0xbd0ebd55,0x3d7d3c16,0xbd463d22,0x3b49bd80,0x3cc43d6d,0xbd71bcac,0x3d62bcf1,0xbc793d78,0xbc48bd7b,0x3d5c3d04,0xbd753c95,0x3cdbbd67,0x3d80,0xbd3ebd2c,0x3d7fbbc9,0xbd183d4e,
0xbd7bbc48,0x3d4ebd18,0xbbc93d7f,0xbd2cbd3e,0x3d6d3cc4,0xbd673cdb,0x3c95bd75,0x3d043d5c,0xbd55bd0e,0x3d78bc79,0xbcf13d62,0xbcacbd71,0x3d353d35,0xbd803b49,0x3d22bd46,0x3c163d7d,
0xbd35bd35,0x3d7d3c16,0xbd623cf1,0x3cdbbd67,0x3c483d7b,0xbd3ebd2c,0x3d7f3bc9,0xbd5c3d04,0x3cc4bd6d,0x3c793d78,0xbd46bd22,0x3d803b49,0xbd553d0e,0x3cacbd71,0x3c953d75,0xbd4ebd18,
0x3d80,0xbd18bd4e,0x3d753c95,0xbd713cac,0x3d0ebd55,0x3b493d80,0xbd22bd46,0x3d783c79,0xbd6d3cc4,0x3d04bd5c,0x3bc93d7f,0xbd2cbd3e,0x3d7b3c48,0xbd673cdb,0x3cf1bd62,0x3c163d7d,
0x3d0ebd55,0xbc163d7d,0xbc95bd75,0x3d2c3d3e,0x3d353d35,0xbd71bcac,0x3d7fbbc9,0xbd5c3d04,0xbc483d7b,0xbc79bd78,0x3d223d46,0xbd67bcdb,0xbd6dbcc4,0x3d80bb49,0xbd623cf1,0x3d18bd4e,
0x3d7bbc48,0xbd4e3d18,0x3cf1bd62,0xbb493d80,0x3d80,0xbcdbbd67,0x3d463d22,0xbd78bc79,0xbd553d0e,0x3d04bd5c,0xbbc93d7f,0xbcacbd71,0xbcc4bd6d,0x3d3e3d2c,0xbd75bc95,0x3d7dbc16,
0xbcc43d6d,0x3c16bd7d,0x3bc93d7f,0xbcacbd71,0x3d0e3d55,0xbd3ebd2c,0x3d623cf1,0xbd78bc79,0xbd35bd35,0x3d5c3d04,0xbd75bc95,0x3d803b49,0xbd7b3c48,0x3d67bcdb,0xbd463d22,0x3d18bd4e,
0x3d6dbcc4,0xbd4e3d18,0x3d22bd46,0xbcdb3d67,0x3c48bd7b,0x3b493d80,0xbc95bd75,0x3d043d5c,0x3d80,0xbc79bd78,0x3cf13d62,0xbd2cbd3e,0x3d553d0e,0xbd71bcac,0x3d7f3bc9,0xbd7d3c16,
0x3d7b3c48,0xbd7dbc16,0x3d7f3bc9,0xbd80bb49,0x3d6d3cc4,0xbd71bcac,0x3d753c95,0xbd78bc79,0x3d553d0e,0xbd5cbd04,0x3d623cf1,0xbd67bcdb,0x3d353d35,0xbd3ebd2c,0x3d463d22,0xbd4ebd18,
0x3d0e3d55,0xbd18bd4e,0x3d223d46,0xbd2cbd3e,0x3cc43d6d,0xbcdbbd67,0x3cf13d62,0xbd04bd5c,0x3c483d7b,0xbc79bd78,0x3c953d75,0xbcacbd71,0x3d80,0xbb49bd80,0x3bc93d7f,0xbc16bd7d,
0xbd800000,0x3c16bd7d,0x3d753c95,0xbcdb3d67,0xbd55bd0e,0x3d2cbd3e,0x3d223d46,0xbd5c3d04,0xbcc4bd6d,0x3d78bc79,0x3bc93d7f,0xbd80bb49,0x3c48bd7b,0x3d713cac,0xbcf13d62,0xbd4ebd18,
0x3d35bd35,0x3d183d4e,0xbd623cf1,0xbcacbd71,0x3d7bbc48,0x3b493d80,0xbd7fbbc9,0x3c79bd78,0x3d6d3cc4,0xbd043d5c,0xbd46bd22,0x3d3ebd2c,0x3d0e3d55,0xbd673cdb,0xbc95bd75,0x3d7dbc16,
0xbc48bd7b,0x3d7d3c16,0xbcf13d62,0xbd2cbd3e,0xbd800000,0x3cacbd71,0x3d463d22,0xbd5c3d04,0x3d0e3d55,0xbd783c79,0x3bc9bd7f,0x3d673cdb,0x3d6dbcc4,0x3b493d80,0xbd75bc95,0x3d18bd4e,
0xbd55bd0e,0x3d4ebd18,0x3c953d75,0xbd80bb49,0xbd353d35,0xbcdbbd67,0x3d7fbbc9,0xbc793d78,0x3d7b3c48,0xbd043d5c,0xbd22bd46,0x3d71bcac,0x3cc4bd6d,0x3d3e3d2c,0xbd623cf1,0xbc16bd7d,
0x3cc43d6d,0xbd7dbc16,0x3d22bd46,0x3cac3d71,0xbd7bbc48,0x3d2cbd3e,0x3c953d75,0xbd78bc79,0xbd800000,0x3d04bd5c,0x3cf13d62,0xbd80bb49,0x3d0ebd55,0x3cdb3d67,0xbd7fbbc9,0x3d18bd4e,
0xbd6dbcc4,0x3d4ebd18,0x3bc93d7f,0xbd67bcdb,0x3d55bd0e,0x3b493d80,0xbd62bcf1,0x3d5cbd04,0x3d35bd35,0x3c793d78,0xbd75bc95,0x3d3ebd2c,0x3c483d7b,0xbd71bcac,0x3d46bd22,0x3c163d7d,
0x3d55bd0e,0xbc163d7d,0xbd22bd46,0x3d803b49,0xbd6d3cc4,0x3cacbd71,0x3cf13d62,0xbd78bc79,0x3d7bbc48,0xbd043d5c,0xbc95bd75,0x3d673cdb,0xbd800000,0x3d2cbd3e,0x3bc93d7f,0xbd4ebd18,
0x3c48bd7b,0x3d183d4e,0xbd7fbbc9,0x3d3ebd2c,0xbcc43d6d,0xbcdbbd67,0x3d753c95,0xbd5c3d04,0x3d0ebd55,0x3c793d78,0xbd62bcf1,0x3d71bcac,0xbd353d35,0xbb49bd80,0x3d463d22,0xbd7d3c16,
0x3d35bd35,0xbc163d7d,0xbcf1bd62,0x3d673cdb,0xbd7b3c48,0x3d2cbd3e,0xbbc93d7f,0xbd04bd5c,0x3d6d3cc4,0xbd783c79,0x3d22bd46,0xbb493d80,0xbd0ebd55,0x3d713cac,0xbd753c95,0x3d18bd4e,
0xbd800000,0x3d4ebd18,0xbc953d75,0xbcacbd71,0x3d553d0e,0xbd803b49,0x3d46bd22,0xbc793d78,0xbcc4bd6d,0x3d5c3d04,0xbd7f3bc9,0x3d3ebd2c,0xbc483d7b,0xbcdbbd67,0x3d623cf1,0xbd7d3c16,
0x3d553d0e,0xbd7dbc16,0x3d75bc95,0xbd3e3d2c,0xbd353d35,0x3cacbd71,0x3bc93d7f,0xbd04bd5c,0xbd7bbc48,0x3d78bc79,0xbd463d22,0x3cdbbd67,0x3cc4bd6d,0x3b493d80,0xbcf1bd62,0x3d4e3d18,
0x3c483d7b,0xbd18bd4e,0x3d623cf1,0xbd80bb49,0xbd800000,0x3d67bcdb,0xbd223d46,0x3c79bd78,0xbd0ebd55,0x3d5c3d04,0xbd7fbbc9,0x3d71bcac,0x3d6dbcc4,0xbd2c3d3e,0x3c95bd75,0x3c163d7d,
0xbd6dbcc4,0x3d7d3c16,0xbd7f3bc9,0x3d71bcac,0xbd553d0e,0x3d2cbd3e,0xbcf13d62,0x3c79bd78,0x3d35bd35,0xbd043d5c,0x3c95bd75,0xbb493d80,0xbc48bd7b,0x3cdb3d67,0xbd22bd46,0x3d4e3d18,
0x3cc43d6d,0xbd18bd4e,0x3d463d22,0xbd67bcdb,0x3d7b3c48,0xbd803b49,0x3d75bc95,0xbd5c3d04,0xbd800000,0x3d78bc79,0xbd623cf1,0x3d3ebd2c,0xbd0e3d55,0x3cacbd71,0xbbc93d7f,0xbc16bd7d,
0xbc483d7b,0x3c16bd7d,0xbbc93d7f,0x3b49bd80,0xbcc43d6d,0x3cacbd71,0xbc953d75,0x3c79bd78,0xbd0e3d55,0x3d04bd5c,0xbcf13d62,0x3cdbbd67,0xbd353d35,0x3d2cbd3e,0xbd223d46,0x3d18bd4e,
0xbd553d0e,0x3d4ebd18,0xbd463d22,0x3d3ebd2c,0xbd6d3cc4,0x3d67bcdb,0xbd623cf1,0x3d5cbd04,0xbd7b3c48,0x3d78bc79,0xbd753c95,0x3d71bcac,0xbd800000,0x3d80bb49,0xbd7f3bc9,0x3d7dbc16,
0x3d80,0x3c16bd7d,0xbc953d75,0x3cdbbd67,0xbd0e3d55,0x3d2cbd3e,0xbd463d22,0x3d5cbd04,0xbd6d3cc4,0x3d78bc79,0xbd7f3bc9,0x3d803b49,0xbd7bbc48,0x3d713cac,0xbd62bcf1,0x3d4e3d18,
0xbd35bd35,0x3d183d4e,0xbcf1bd62,0x3cac3d71,0xbc48bd7b,0x3b493d80,0x3bc9bd7f,0xbc793d78,0x3cc4bd6d,0xbd043d5c,0x3d22bd46,0xbd3e3d2c,0x3d55bd0e,0xbd673cdb,0x3d75bc95,0xbd7d3c16,
0xbd7b3c48,0x3d7d3c16,0xbd62bcf1,0x3d2c3d3e,0x3d80,0x3cacbd71,0xbd223d46,0x3d5cbd04,0x3d55bd0e,0xbd783c79,0x3d7f3bc9,0xbd67bcdb,0xbcc4bd6d,0x3b493d80,0x3c95bd75,0xbd183d4e,
0xbd0e3d55,0x3d4ebd18,0xbd753c95,0x3d803b49,0x3d353d35,0xbcdbbd67,0x3bc93d7f,0x3c79bd78,0x3c48bd7b,0xbd043d5c,0x3d46bd22,0xbd713cac,0xbd6dbcc4,0x3d3e3d2c,0xbcf1bd62,0x3c163d7d,
0x3d6dbcc4,0xbd7dbc16,0x3d463d22,0xbcacbd71,0xbc483d7b,0x3d2cbd3e,0xbd753c95,0x3d783c79,0x3d80,0x3d04bd5c,0xbd623cf1,0x3d803b49,0xbd55bd0e,0x3cdb3d67,0x3bc9bd7f,0xbd183d4e,
0xbcc43d6d,0x3d4ebd18,0xbd7f3bc9,0x3d673cdb,0xbd0ebd55,0x3b493d80,0x3cf1bd62,0xbd5c3d04,0xbd35bd35,0x3c793d78,0x3c95bd75,0xbd3e3d2c,0x3d7bbc48,0xbd71bcac,0x3d223d46,0xbc16bd7d,
0xbd0ebd55,0xbc163d7d,0x3d46bd22,0xbd80bb49,0x3cc43d6d,0x3cacbd71,0xbd623cf1,0x3d783c79,0xbc48bd7b,0xbd043d5c,0x3d75bc95,0xbd67bcdb,0x3d80,0x3d2cbd3e,0xbd7f3bc9,0x3d4e3d18,
0xbd7bbc48,0x3d183d4e,0x3bc9bd7f,0xbd3e3d2c,0x3d6d3cc4,0xbcdbbd67,0xbc953d75,0x3d5cbd04,0xbd55bd0e,0x3c793d78,0x3cf1bd62,0xbd713cac,0x3d353d35,0xbb49bd80,0xbd223d46,0x3d7dbc16,
0xbd35bd35,0xbc163d7d,0x3d62bcf1,0xbd67bcdb,0x3c483d7b,0x3d2cbd3e,0xbd7fbbc9,0x3d043d5c,0x3cc4bd6d,0xbd783c79,0x3d463d22,0x3b49bd80,0xbd553d0e,0x3d713cac,0xbc95bd75,0xbd183d4e,
0x3d80,0x3d4ebd18,0xbd75bc95,0x3cac3d71,0x3d0ebd55,0xbd803b49,0x3d223d46,0x3c79bd78,0xbd6d3cc4,0x3d5c3d04,0xbbc9bd7f,0xbd3e3d2c,0x3d7b3c48,0xbcdbbd67,0xbcf13d62,0x3d7dbc16,
0x3d0ebd55,0xbd7dbc16,0x3c953d75,0x3d3ebd2c,0x3d353d35,0x3cacbd71,0xbd7f3bc9,0x3d043d5c,0xbc483d7b,0x3d78bc79,0xbd22bd46,0xbcdb3d67,0xbd6dbcc4,0x3b493d80,0x3d62bcf1,0xbd4ebd18,
0x3d7bbc48,0xbd18bd4e,0xbcf13d62,0x3d803b49,0x3d80,0x3d67bcdb,0xbd46bd22,0xbc793d78,0xbd553d0e,0x3d5c3d04,0x3bc9bd7f,0xbd713cac,0xbcc4bd6d,0xbd2c3d3e,0x3d753c95,0xbc16bd7d,
0xbcc43d6d,0x3d7d3c16,0xbbc9bd7f,0xbd713cac,0x3d0e3d55,0x3d2cbd3e,0xbd62bcf1,0xbc793d78,0xbd35bd35,0xbd043d5c,0x3d753c95,0x3b49bd80,0xbd7b3c48,0x3cdb3d67,0x3d46bd22,0xbd4ebd18,
0x3d6dbcc4,0xbd18bd4e,0xbd223d46,0x3d673cdb,0x3c48bd7b,0xbd803b49,0x3c953d75,0x3d5cbd04,0x3d80,0x3d78bc79,0xbcf1bd62,0xbd3e3d2c,0x3d553d0e,0x3cacbd71,0xbd7fbbc9,0x3c163d7d,
0x3d7b3c48,0x3c16bd7d,0xbd7fbbc9,0xbb493d80,0x3d6d3cc4,0x3cacbd71,0xbd75bc95,0xbc793d78,0x3d553d0e,0x3d04bd5c,0xbd62bcf1,0xbcdb3d67,0x3d353d35,0x3d2cbd3e,0xbd46bd22,0xbd183d4e,
0x3d0e3d55,0x3d4ebd18,0xbd22bd46,0xbd3e3d2c,0x3cc43d6d,0x3d67bcdb,0xbcf1bd62,0xbd5c3d04,0x3c483d7b,0x3d78bc79,0xbc95bd75,0xbd713cac,0x3d80,0x3d80bb49,0xbbc9bd7f,0xbd7d3c16,
0xbd800000,0x3d7d3c16,0xbd75bc95,0x3d673cdb,0xbd55bd0e,0x3d3e3d2c,0xbd22bd46,0x3d043d5c,0xbcc4bd6d,0x3c793d78,0xbbc9bd7f,0xbb493d80,0x3c48bd7b,0xbcac3d71,0x3cf1bd62,0xbd183d4e,
0x3d35bd35,0xbd4e3d18,0x3d62bcf1,0xbd713cac,0x3d7bbc48,0xbd803b49,0x3d7f3bc9,0xbd78bc79,0x3d6d3cc4,0xbd5cbd04,0x3d463d22,0xbd2cbd3e,0x3d0e3d55,0xbcdbbd67,0x3c953d75,0xbc16bd7d,
0xbc48bd7b,0xbc163d7d,0x3cf1bd62,0xbd3e3d2c,0xbd800000,0x3d713cac,0xbd46bd22,0x3d043d5c,0x3d0e3d55,0xbc79bd78,0xbbc93d7f,0x3cdbbd67,0x3d6dbcc4,0xbd803b49,0x3d753c95,0xbd4ebd18,
0xbd55bd0e,0x3d183d4e,0xbc95bd75,0xbb493d80,0xbd353d35,0x3d67bcdb,0xbd7f3bc9,0x3d783c79,0x3d7b3c48,0xbd5cbd04,0x3d223d46,0xbcacbd71,0x3cc4bd6d,0xbd2c3d3e,0x3d62bcf1,0xbd7d3c16,
0x3cc43d6d,0x3c16bd7d,0xbd223d46,0x3d71bcac,0xbd7bbc48,0x3d3e3d2c,0xbc95bd75,0xbc793d78,0xbd800000,0x3d5c3d04,0xbcf1bd62,0xbb493d80,0x3d0ebd55,0xbd673cdb,0x3d7f3bc9,0xbd4ebd18,
0xbd6dbcc4,0x3d183d4e,0xbbc9bd7f,0xbcdb3d67,0x3d55bd0e,0xbd803b49,0x3d623cf1,0xbd04bd5c,0x3d35bd35,0xbd783c79,0x3d753c95,0xbd2cbd3e,0x3c483d7b,0x3cacbd71,0xbd463d22,0x3d7dbc16,
0x3d55bd0e,0xbd7dbc16,0x3d223d46,0x3b49bd80,0xbd6d3cc4,0x3d713cac,0xbcf1bd62,0xbc793d78,0x3d7bbc48,0xbd5cbd04,0x3c953d75,0x3cdbbd67,0xbd800000,0x3d3e3d2c,0xbbc9bd7f,0xbd183d4e,
0x3c48bd7b,0xbd4e3d18,0x3d7f3bc9,0xbd2cbd3e,0xbcc43d6d,0x3d67bcdb,0xbd75bc95,0x3d043d5c,0x3d0ebd55,0xbd783c79,0x3d623cf1,0xbcacbd71,0xbd353d35,0x3d80bb49,0xbd46bd22,0x3c163d7d,
0x3d35bd35,0xbd7dbc16,0x3cf13d62,0x3cdbbd67,0xbd7b3c48,0x3d3e3d2c,0x3bc9bd7f,0xbd5c3d04,0x3d6d3cc4,0xbc79bd78,0xbd223d46,0x3d803b49,0xbd0ebd55,0xbcac3d71,0x3d75bc95,0xbd4ebd18,
0xbd800000,0x3d183d4e,0x3c95bd75,0xbd713cac,0x3d553d0e,0xbb49bd80,0xbd463d22,0x3d783c79,0xbcc4bd6d,0xbd043d5c,0x3d7fbbc9,0xbd2cbd3e,0xbc483d7b,0x3d67bcdb,0xbd62bcf1,0x3c163d7d,
0x3d553d0e,0x3c16bd7d,0xbd753c95,0x3d2c3d3e,0xbd353d35,0x3d713cac,0xbbc9bd7f,0xbd5c3d04,0xbd7bbc48,0x3c793d78,0x3d46bd22,0xbd67bcdb,0x3cc4bd6d,0xbd803b49,0x3cf13d62,0x3d18bd4e,
0x3c483d7b,0x3d4ebd18,0xbd62bcf1,0xbb493d80,0xbd800000,0x3cdb3d67,0x3d22bd46,0xbd78bc79,0xbd0ebd55,0xbd043d5c,0x3d7f3bc9,0xbcacbd71,0x3d6dbcc4,0xbd3ebd2c,0xbc953d75,0x3d7dbc16,
0xbd6dbcc4,0xbc163d7d,0x3d7fbbc9,0xbcacbd71,0xbd553d0e,0x3d3e3d2c,0x3cf1bd62,0xbd78bc79,0x3d35bd35,0xbd5cbd04,0xbc953d75,0x3d803b49,0xbc48bd7b,0xbd673cdb,0x3d223d46,0x3d18bd4e,
0x3cc43d6d,0x3d4ebd18,0xbd46bd22,0xbcdb3d67,0x3d7b3c48,0xbb49bd80,0xbd753c95,0x3d043d5c,0xbd800000,0x3c793d78,0x3d62bcf1,0xbd2cbd3e,0xbd0e3d55,0x3d713cac,0x3bc9bd7f,0xbd7d3c16,
0xbc483d7b,0x3d7d3c16,0x3bc9bd7f,0xbd80bb49,0xbcc43d6d,0x3d713cac,0x3c95bd75,0xbd78bc79,0xbd0e3d55,0x3d5c3d04,0x3cf1bd62,0xbd67bcdb,0xbd353d35,0x3d3e3d2c,0x3d22bd46,0xbd4ebd18,
0xbd553d0e,0x3d183d4e,0x3d46bd22,0xbd2cbd3e,0xbd6d3cc4,0x3cdb3d67,0x3d62bcf1,0xbd04bd5c,0xbd7b3c48,0x3c793d78,0x3d75bc95,0xbcacbd71,0xbd800000,0x3b493d80,0x3d7fbbc9,0xbc16bd7d,
0x3d80,0x3d7d3c16,0x3c95bd75,0xbd67bcdb,0xbd0e3d55,0x3d3e3d2c,0x3d46bd22,0xbd04bd5c,0xbd6d3cc4,0x3c793d78,0x3d7fbbc9,0x3b49bd80,0xbd7bbc48,0xbcac3d71,0x3d623cf1,0x3d18bd4e,
0xbd35bd35,0xbd4e3d18,0x3cf13d62,0x3d71bcac,0xbc48bd7b,0xbd803b49,0xbbc93d7f,0x3d783c79,0x3cc4bd6d,0xbd5cbd04,0xbd223d46,0x3d2c3d3e,0x3d55bd0e,0xbcdbbd67,0xbd753c95,0x3c163d7d,
0xbd7b3c48,0xbc163d7d,0x3d623cf1,0x3d3ebd2c,0x3d80,0x3d713cac,0x3d22bd46,0xbd04bd5c,0x3d55bd0e,0xbc79bd78,0xbd7fbbc9,0xbcdb3d67,0xbcc4bd6d,0xbd803b49,0xbc953d75,0x3d4e3d18,
0xbd0e3d55,0x3d183d4e,0x3d75bc95,0x3b49bd80,0x3d353d35,0x3d67bcdb,0xbbc9bd7f,0xbd78bc79,0x3c48bd7b,0xbd5cbd04,0xbd463d22,0x3cac3d71,0xbd6dbcc4,0xbd2c3d3e,0x3cf13d62,0x3d7dbc16,
0x3d6dbcc4,0x3c16bd7d,0xbd46bd22,0xbd713cac,0xbc483d7b,0x3d3e3d2c,0x3d75bc95,0x3c79bd78,0x3d80,0x3d5c3d04,0x3d62bcf1,0x3b49bd80,0xbd55bd0e,0xbd673cdb,0xbbc93d7f,0x3d4e3d18,
0xbcc43d6d,0x3d183d4e,0x3d7fbbc9,0x3cdbbd67,0xbd0ebd55,0xbd803b49,0xbcf13d62,0x3d043d5c,0xbd35bd35,0xbd783c79,0xbc953d75,0x3d2c3d3e,0x3d7bbc48,0x3cacbd71,0xbd22bd46,0xbd7d3c16,
0xbd0ebd55,0xbd7dbc16,0xbd463d22,0xbb493d80,0x3cc43d6d,0x3d713cac,0x3d62bcf1,0x3c79bd78,0xbc48bd7b,0xbd5cbd04,0xbd753c95,0xbcdb3d67,0x3d80,0x3d3e3d2c,0x3d7fbbc9,0x3d18bd4e,
0xbd7bbc48,0xbd4e3d18,0xbbc93d7f,0x3d2c3d3e,0x3d6d3cc4,0x3d67bcdb,0x3c95bd75,0xbd04bd5c,0xbd55bd0e,0xbd783c79,0xbcf13d62,0x3cac3d71,0x3d353d35,0x3d80bb49,0x3d22bd46,0xbc16bd7d,
0xbd35bd35,0xbd7dbc16,0xbd623cf1,0xbcdb3d67,0x3c483d7b,0x3d3e3d2c,0x3d7f3bc9,0x3d5cbd04,0x3cc4bd6d,0xbc79bd78,0xbd46bd22,0xbd80bb49,0xbd553d0e,0xbcac3d71,0x3c953d75,0x3d4e3d18,
0x3d80,0x3d183d4e,0x3d753c95,0x3d71bcac,0x3d0ebd55,0xbb49bd80,0xbd22bd46,0xbd78bc79,0xbd6d3cc4,0xbd043d5c,0x3bc93d7f,0x3d2c3d3e,0x3d7b3c48,0x3d67bcdb,0x3cf1bd62,0xbc16bd7d,
0x3d0ebd55,0x3c16bd7d,0xbc95bd75,0xbd2cbd3e,0x3d353d35,0x3d713cac,0x3d7fbbc9,0x3d5cbd04,0xbc483d7b,0x3c793d78,0x3d223d46,0x3d673cdb,0xbd6dbcc4,0xbd803b49,0xbd623cf1,0xbd183d4e,
0x3d7bbc48,0x3d4ebd18,0x3cf1bd62,0x3b49bd80,0x3d80,0x3cdb3d67,0x3d463d22,0x3d783c79,0xbd553d0e,0xbd043d5c,0xbbc93d7f,0x3cac3d71,0xbcc4bd6d,0xbd3ebd2c,0xbd75bc95,0xbd7d3c16,
0xbcc43d6d,0xbc163d7d,0x3bc93d7f,0x3cac3d71,0x3d0e3d55,0x3d3e3d2c,0x3d623cf1,0x3d783c79,0xbd35bd35,0xbd5cbd04,0xbd75bc95,0xbd80bb49,0xbd7b3c48,0xbd673cdb,0xbd463d22,0xbd183d4e,
0x3d6dbcc4,0x3d4ebd18,0x3d22bd46,0x3cdbbd67,0x3c48bd7b,0xbb49bd80,0xbc95bd75,0xbd04bd5c,0x3d80,0x3c793d78,0x3cf13d62,0x3d2c3d3e,0x3d553d0e,0x3d713cac,0x3d7f3bc9,0x3d7dbc16,
0x3d7b3c48,0x3d7d3c16,0x3d7f3bc9,0x3d803b49,0x3d6d3cc4,0x3d713cac,0x3d753c95,0x3d783c79,0x3d553d0e,0x3d5c3d04,0x3d623cf1,0x3d673cdb,0x3d353d35,0x3d3e3d2c,0x3d463d22,0x3d4e3d18,
0x3d0e3d55,0x3d183d4e,0x3d223d46,0x3d2c3d3e,0x3cc43d6d,0x3cdb3d67,0x3cf13d62,0x3d043d5c,0x3c483d7b,0x3c793d78,0x3c953d75,0x3cac3d71,0x3d80,0x3b493d80,0x3bc93d7f,0x3c163d7d,
0xbd800000,0xbc163d7d,0x3d753c95,0x3cdbbd67,0xbd55bd0e,0xbd2c3d3e,0x3d223d46,0x3d5cbd04,0xbcc4bd6d,0xbd783c79,0x3bc93d7f,0x3d803b49,0x3c48bd7b,0xbd71bcac,0xbcf13d62,0x3d4e3d18,
0x3d35bd35,0xbd18bd4e,0xbd623cf1,0x3cac3d71,0x3d7bbc48,0xbb49bd80,0xbd7fbbc9,0xbc793d78,0x3d6d3cc4,0x3d04bd5c,0xbd46bd22,0xbd3e3d2c,0x3d0e3d55,0x3d67bcdb,0xbc95bd75,0xbd7d3c16,
0xbc48bd7b,0xbd7dbc16,0xbcf13d62,0x3d2c3d3e,0xbd800000,0xbcac3d71,0x3d463d22,0x3d5cbd04,0x3d0e3d55,0x3d78bc79,0x3bc9bd7f,0xbd67bcdb,0x3d6dbcc4,0xbb49bd80,0xbd75bc95,0xbd183d4e,
0xbd55bd0e,0xbd4e3d18,0x3c953d75,0x3d803b49,0xbd353d35,0x3cdb3d67,0x3d7fbbc9,0x3c79bd78,0x3d7b3c48,0x3d04bd5c,0xbd22bd46,0xbd713cac,0x3cc4bd6d,0xbd3ebd2c,0xbd623cf1,0x3c163d7d,
0x3cc43d6d,0x3d7d3c16,0x3d22bd46,0xbcacbd71,0xbd7bbc48,0xbd2c3d3e,0x3c953d75,0x3d783c79,0xbd800000,0xbd043d5c,0x3cf13d62,0x3d803b49,0x3d0ebd55,0xbcdbbd67,0xbd7fbbc9,0xbd183d4e,
0xbd6dbcc4,0xbd4e3d18,0x3bc93d7f,0x3d673cdb,0x3d55bd0e,0xbb49bd80,0xbd62bcf1,0xbd5c3d04,0x3d35bd35,0xbc79bd78,0xbd75bc95,0xbd3e3d2c,0x3c483d7b,0x3d713cac,0x3d46bd22,0xbc16bd7d,
0x3d55bd0e,0x3c16bd7d,0xbd22bd46,0xbd80bb49,0xbd6d3cc4,0xbcac3d71,0x3cf13d62,0x3d783c79,0x3d7bbc48,0x3d04bd5c,0xbc95bd75,0xbd67bcdb,0xbd800000,0xbd2c3d3e,0x3bc93d7f,0x3d4e3d18,
0x3c48bd7b,0xbd18bd4e,0xbd7fbbc9,0xbd3e3d2c,0xbcc43d6d,0x3cdb3d67,0x3d753c95,0x3d5cbd04,0x3d0ebd55,0xbc79bd78,0xbd62bcf1,0xbd713cac,0xbd353d35,0x3b493d80,0x3d463d22,0x3d7dbc16,
0x3d35bd35,0x3c16bd7d,0xbcf1bd62,0xbd67bcdb,0xbd7b3c48,0xbd2c3d3e,0xbbc93d7f,0x3d043d5c,0x3d6d3cc4,0x3d78bc79,0x3d22bd46,0x3b49bd80,0xbd0ebd55,0xbd71bcac,0xbd753c95,0xbd183d4e,
0xbd800000,0xbd4e3d18,0xbc953d75,0x3cac3d71,0x3d553d0e,0x3d80bb49,0x3d46bd22,0x3c79bd78,0xbcc4bd6d,0xbd5cbd04,0xbd7f3bc9,0xbd3e3d2c,0xbc483d7b,0x3cdb3d67,0x3d623cf1,0x3d7dbc16,
0x3d553d0e,0x3d7d3c16,0x3d75bc95,0x3d3ebd2c,0xbd353d35,0xbcac3d71,0x3bc93d7f,0x3d043d5c,0xbd7bbc48,0xbd783c79,0xbd463d22,0xbcdb3d67,0x3cc4bd6d,0xbb49bd80,0xbcf1bd62,0xbd4ebd18,
0x3c483d7b,0x3d183d4e,0x3d623cf1,0x3d803b49,0xbd800000,0xbd673cdb,0xbd223d46,0xbc793d78,0xbd0ebd55,0xbd5cbd04,0xbd7fbbc9,0xbd713cac,0x3d6dbcc4,0x3d2cbd3e,0x3c95bd75,0xbc16bd7d,
0xbd6dbcc4,0xbd7dbc16,0xbd7f3bc9,0xbd713cac,0xbd553d0e,0xbd2c3d3e,0xbcf13d62,0xbc793d78,0x3d35bd35,0x3d04bd5c,0x3c95bd75,0x3b49bd80,0xbc48bd7b,0xbcdbbd67,0xbd22bd46,0xbd4ebd18,
0x3cc43d6d,0x3d183d4e,0x3d463d22,0x3d673cdb,0x3d7b3c48,0x3d80bb49,0x3d75bc95,0x3d5cbd04,0xbd800000,0xbd783c79,0xbd623cf1,0xbd3e3d2c,0xbd0e3d55,0xbcac3d71,0xbbc93d7f,0x3c163d7d,
0xbc483d7b,0xbc163d7d,0xbbc93d7f,0xbb493d80,0xbcc43d6d,0xbcac3d71,0xbc953d75,0xbc793d78,0xbd0e3d55,0xbd043d5c,0xbcf13d62,0xbcdb3d67,0xbd353d35,0xbd2c3d3e,0xbd223d46,0xbd183d4e,
0xbd553d0e,0xbd4e3d18,0xbd463d22,0xbd3e3d2c,0xbd6d3cc4,0xbd673cdb,0xbd623cf1,0xbd5c3d04,0xbd7b3c48,0xbd783c79,0xbd753c95,0xbd713cac,0xbd800000,0xbd803b49,0xbd7f3bc9,0xbd7d3c16,
0x3f003f00,0xbf003f00,0x3f003f00,0xbf003f00,0x3f003f00,0xbf003f00,0x3f003f00,0xbf003f00,0x3f003f00,0xbf003f00,0x3f003f00,0xbf003f00,0x3f003f00,0xbf003f00,0x3f003f00,0xbf003f00,
0x3eff3f00,0xbd490000,0x3ea23eb5,0xbec6beb5,0x3ef53efb,0xbe15bdc8,0x3e713e8e,0xbee2bed5,0x3ee23eed,0xbe71be44,0x3e153e44,0xbef5beed,0x3ec63ed5,0xbea2be8e,0x3d493dc8,0xbeffbefb,
0x3efb3f00,0xbdc80000,0xbdc80000,0xbefbbf00,0x3ed53eed,0xbe8ebe44,0xbe8ebe44,0xbed5beed,0x3e8e3eb5,0xbed5beb5,0xbed5beb5,0xbe8ebeb5,0x3dc83e44,0xbefbbeed,0xbefbbeed,0xbdc8be44,
0x3ef53f00,0xbe150000,0xbee2beb5,0xbe71beb5,0x3ea23ed5,0xbec6be8e,0xbeffbefb,0x3d49bdc8,0x3d493e44,0xbeffbeed,0xbec6beed,0x3ea23e44,0xbe71bdc8,0xbee2befb,0xbe15be8e,0x3ef53ed5,
0x3eed3f00,0xbe440000,0xbeedbf00,0x3e440000,0x3e443eb5,0xbeedbeb5,0xbe44beb5,0x3eed3eb5,0xbe440000,0xbeedbf00,0x3e440000,0x3eed3f00,0xbeedbeb5,0xbe44beb5,0x3eed3eb5,0x3e443eb5,
0x3ee23f00,0xbe710000,0xbe15beb5,0x3ef53eb5,0x3d493e8e,0xbeffbed5,0x3ea23dc8,0x3ec63efb,0xbec6be44,0xbea2beed,0x3eff3eed,0xbd493e44,0xbef5befb,0x3e15bdc8,0x3e713ed5,0xbee2be8e,
0x3ed53f00,0xbe8e0000,0x3e8e0000,0x3ed53f00,0xbdc83e44,0xbefbbeed,0x3efb3eed,0xbdc83e44,0xbefbbeb5,0xbdc8beb5,0x3dc83eb5,0xbefbbeb5,0xbe8ebeed,0x3ed53e44,0xbed5be44,0xbe8ebeed,
0x3ec63f00,0xbea20000,0x3eff3eb5,0x3d493eb5,0xbe713dc8,0xbee2befb,0x3e153ed5,0xbef5be8e,0xbef5beed,0x3e15be44,0xbee2be44,0xbe71beed,0x3d49be8e,0x3eff3ed5,0xbea2befb,0x3ec63dc8,
0x3f00,0xbf000000,0x3f00,0xbf000000,0xbf00,0x3f000000,0xbf00,0x3f000000,0x3f00,0xbf000000,0x3f00,0xbf000000,0xbf00,0x3f000000,0xbf00,0x3f000000,
0xbd493f00,0xbeff0000,0xbec63eb5,0xbea2beb5,0x3e15befb,0x3ef53dc8,0x3ee2be8e,0x3e713ed5,0xbe713eed,0xbee2be44,0xbef53e44,0xbe15beed,0x3ea2bed5,0x3ec63e8e,0x3effbdc8,0x3d493efb,
0xbdc83f00,0xbefb0000,0xbefb0000,0x3dc8bf00,0x3e8ebeed,0x3ed53e44,0x3ed53e44,0xbe8e3eed,0xbed53eb5,0xbe8ebeb5,0xbe8ebeb5,0x3ed5beb5,0x3efbbe44,0x3dc83eed,0x3dc83eed,0xbefb3e44,
0xbe153f00,0xbef50000,0xbe71beb5,0x3ee2beb5,0x3ec6bed5,0x3ea23e8e,0xbd493efb,0xbeff3dc8,0xbeff3e44,0xbd49beed,0x3ea2beed,0x3ec63e44,0x3ee23dc8,0xbe713efb,0xbef53e8e,0xbe15bed5,
0xbe443f00,0xbeed0000,0x3e44bf00,0x3eed0000,0x3eedbeb5,0x3e443eb5,0xbeed3eb5,0xbe44beb5,0xbeed0000,0x3e44bf00,0x3eed0000,0xbe443f00,0x3e443eb5,0xbeed3eb5,0xbe44beb5,0x3eedbeb5,
0xbe713f00,0xbee20000,0x3ef5beb5,0x3e153eb5,0x3effbe8e,0x3d493ed5,0xbec6bdc8,0x3ea2befb,0xbea2be44,0x3ec6beed,0xbd493eed,0xbeff3e44,0xbe153efb,0xbef53dc8,0x3ee2bed5,0x3e713e8e,
0xbe8e3f00,0xbed50000,0x3ed50000,0xbe8e3f00,0x3efbbe44,0xbdc83eed,0x3dc8beed,0x3efbbe44,0xbdc8beb5,0x3efbbeb5,0xbefb3eb5,0xbdc8beb5,0xbed53eed,0xbe8ebe44,0x3e8e3e44,0xbed53eed,
0xbea23f00,0xbec60000,0x3d493eb5,0xbeff3eb5,0x3ee2bdc8,0xbe713efb,0x3ef5bed5,0x3e153e8e,0x3e15beed,0x3ef5be44,0xbe71be44,0x3ee2beed,0xbeff3e8e,0x3d49bed5,0xbec63efb,0xbea2bdc8,
0x3eb53f00,0xbeb50000,0x3eb53f00,0xbeb50000,0xbeb50000,0xbeb5bf00,0xbeb50000,0xbeb5bf00,0xbeb5bf00,0x3eb50000,0xbeb5bf00,0x3eb50000,0x3eb50000,0x3eb53f00,0x3eb50000,0x3eb53f00,
0xbeff3f00,0x3d490000,0xbea23eb5,0x3ec6beb5,0xbef53efb,0x3e15bdc8,0xbe713e8e,0x3ee2bed5,0xbee23eed,0x3e71be44,0xbe153e44,0x3ef5beed,0xbec63ed5,0x3ea2be8e,0xbd493dc8,0x3effbefb,
0xbefb3f00,0x3dc80000,0x3dc80000,0x3efbbf00,0xbed53eed,0x3e8ebe44,0x3e8ebe44,0x3ed5beed,0xbe8e3eb5,0x3ed5beb5,0x3ed5beb5,0x3e8ebeb5,0xbdc83e44,0x3efbbeed,0x3efbbeed,0x3dc8be44,
0xbef53f00,0x3e150000,0x3ee2beb5,0x3e71beb5,0xbea23ed5,0x3ec6be8e,0x3effbefb,0xbd49bdc8,0xbd493e44,0x3effbeed,0x3ec6beed,0xbea23e44,0x3e71bdc8,0x3ee2befb,0x3e15be8e,0xbef53ed5,
0xbeed3f00,0x3e440000,0x3eedbf00,0xbe440000,0xbe443eb5,0x3eedbeb5,0x3e44beb5,0xbeed3eb5,0x3e440000,0x3eedbf00,0xbe440000,0xbeed3f00,0x3eedbeb5,0x3e44beb5,0xbeed3eb5,0xbe443eb5,
0xbee23f00,0x3e710000,0x3e15beb5,0xbef53eb5,0xbd493e8e,0x3effbed5,0xbea23dc8,0xbec63efb,0x3ec6be44,0x3ea2beed,0xbeff3eed,0x3d493e44,0x3ef5befb,0xbe15bdc8,0xbe713ed5,0x3ee2be8e,
0xbed53f00,0x3e8e0000,0xbe8e0000,0xbed53f00,0x3dc83e44,0x3efbbeed,0xbefb3eed,0x3dc83e44,0x3efbbeb5,0x3dc8beb5,0xbdc83eb5,0x3efbbeb5,0x3e8ebeed,0xbed53e44,0x3ed5be44,0x3e8ebeed,
0xbec63f00,0x3ea20000,0xbeff3eb5,0xbd493eb5,0x3e713dc8,0x3ee2befb,0xbe153ed5,0x3ef5be8e,0x3ef5beed,0xbe15be44,0x3ee2be44,0x3e71beed,0xbd49be8e,0xbeff3ed5,0x3ea2befb,0xbec63dc8,
0xbeb53f00,0xbeb50000,0xbeb53f00,0xbeb50000,0x3eb50000,0xbeb53f00,0x3eb50000,0xbeb53f00,0x3eb5bf00,0x3eb50000,0x3eb5bf00,0x3eb50000,0xbeb50000,0x3eb5bf00,0xbeb50000,0x3eb5bf00,
0x3d493f00,0x3eff0000,0x3ec63eb5,0x3ea2beb5,0xbe15befb,0xbef53dc8,0xbee2be8e,0xbe713ed5,0x3e713eed,0x3ee2be44,0x3ef53e44,0x3e15beed,0xbea2bed5,0xbec63e8e,0xbeffbdc8,0xbd493efb,
0x3dc83f00,0x3efb0000,0x3efb0000,0xbdc8bf00,0xbe8ebeed,0xbed53e44,0xbed53e44,0x3e8e3eed,0x3ed53eb5,0x3e8ebeb5,0x3e8ebeb5,0xbed5beb5,0xbefbbe44,0xbdc83eed,0xbdc83eed,0x3efb3e44,
0x3e153f00,0x3ef50000,0x3e71beb5,0xbee2beb5,0xbec6bed5,0xbea23e8e,0x3d493efb,0x3eff3dc8,0x3eff3e44,0x3d49beed,0xbea2beed,0xbec63e44,0xbee23dc8,0x3e713efb,0x3ef53e8e,0x3e15bed5,
0x3e443f00,0x3eed0000,0xbe44bf00,0xbeed0000,0xbeedbeb5,0xbe443eb5,0x3eed3eb5,0x3e44beb5,0x3eed0000,0xbe44bf00,0xbeed0000,0x3e443f00,0xbe443eb5,0x3eed3eb5,0x3e44beb5,0xbeedbeb5,
0x3e713f00,0x3ee20000,0xbef5beb5,0xbe153eb5,0xbeffbe8e,0xbd493ed5,0x3ec6bdc8,0xbea2befb,0x3ea2be44,0xbec6beed,0x3d493eed,0x3eff3e44,0x3e153efb,0x3ef53dc8,0xbee2bed5,0xbe713e8e,
0x3e8e3f00,0x3ed50000,0xbed50000,0x3e8e3f00,0xbefbbe44,0x3dc83eed,0xbdc8beed,0xbefbbe44,0x3dc8beb5,0xbefbbeb5,0x3efb3eb5,0x3dc8beb5,0x3ed53eed,0x3e8ebe44,0xbe8e3e44,0x3ed53eed,
0x3ea23f00,0x3ec60000,0xbd493eb5,0x3eff3eb5,0xbee2bdc8,0x3e713efb,0xbef5bed5,0xbe153e8e,0xbe15beed,0xbef5be44,0x3e71be44,0xbee2beed,0x3eff3e8e,0xbd49bed5,0x3ec63efb,0x3ea2bdc8,
0x3f003f00,0xbf003f00,0x3f003f00,0xbf003f00,0x3f003f00,0xbf003f00,0x3f003f00,0xbf003f00,0x3f003f00,0xbf003f00,0x3f003f00,0xbf003f00,0x3f003f00,0xbf003f00,0x3f003f00,0xbf003f00,
0xbd490000,0xbeffbf00,0xbec6beb5,0xbea2beb5,0xbe15bdc8,0xbef5befb,0xbee2bed5,0xbe71be8e,0xbe71be44,0xbee2beed,0xbef5beed,0xbe15be44,0xbea2be8e,0xbec6bed5,0xbeffbefb,0xbd49bdc8,
0xbefbbf00,0x3dc80000,0x3dc80000,0x3efb3f00,0xbed5beed,0x3e8e3e44,0x3e8e3e44,0x3ed53eed,0xbe8ebeb5,0x3ed53eb5,0x3ed53eb5,0x3e8e3eb5,0xbdc8be44,0x3efb3eed,0x3efb3eed,0x3dc83e44,
0x3e150000,0x3ef53f00,0x3e713eb5,0xbee2beb5,0x3ec63e8e,0x3ea23ed5,0xbd493dc8,0xbeffbefb,0x3eff3eed,0x3d493e44,0xbea2be44,0xbec6beed,0x3ee23efb,0xbe71bdc8,0xbef5bed5,0xbe15be8e,
0x3eed3f00,0xbe440000,0xbeedbf00,0x3e440000,0x3e443eb5,0xbeedbeb5,0xbe44beb5,0x3eed3eb5,0xbe440000,0xbeedbf00,0x3e440000,0x3eed3f00,0xbeedbeb5,0xbe44beb5,0x3eed3eb5,0x3e443eb5,
0xbe710000,0xbee2bf00,0x3ef53eb5,0x3e153eb5,0xbeffbed5,0xbd49be8e,0x3ec63efb,0xbea2bdc8,0xbea2beed,0x3ec63e44,0xbd493e44,0xbeffbeed,0x3e15bdc8,0x3ef53efb,0xbee2be8e,0xbe71bed5,
0xbed5bf00,0x3e8e0000,0xbe8e0000,0xbed5bf00,0x3dc8be44,0x3efb3eed,0xbefbbeed,0x3dc8be44,0x3efb3eb5,0x3dc83eb5,0xbdc8beb5,0x3efb3eb5,0x3e8e3eed,0xbed5be44,0x3ed53e44,0x3e8e3eed,
0x3ea20000,0x3ec63f00,0xbd49beb5,0x3eff3eb5,0x3ee23efb,0xbe713dc8,0x3ef53e8e,0x3e153ed5,0xbe153e44,0xbef5beed,0x3e713eed,0xbee2be44,0xbeffbed5,0x3d49be8e,0xbec6bdc8,0xbea2befb,
0x3f00,0xbf000000,0x3f00,0xbf000000,0xbf00,0x3f000000,0xbf00,0x3f000000,0x3f00,0xbf000000,0x3f00,0xbf000000,0xbf00,0x3f000000,0xbf00,0x3f000000,
0xbeff0000,0x3d49bf00,0xbea2beb5,0x3ec6beb5,0x3ef53dc8,0xbe153efb,0x3e713ed5,0xbee23e8e,0xbee2be44,0x3e71beed,0xbe15beed,0x3ef5be44,0x3ec63e8e,0xbea23ed5,0x3d493efb,0xbeff3dc8,
0x3dc8bf00,0x3efb0000,0x3efb0000,0xbdc83f00,0xbe8e3eed,0xbed5be44,0xbed5be44,0x3e8ebeed,0x3ed5beb5,0x3e8e3eb5,0x3e8e3eb5,0xbed53eb5,0xbefb3e44,0xbdc8beed,0xbdc8beed,0x3efbbe44,
0x3ef50000,0xbe153f00,0xbee23eb5,0xbe71beb5,0xbea2be8e,0x3ec6bed5,0x3effbdc8,0xbd493efb,0x3d493eed,0xbeff3e44,0xbec6be44,0x3ea2beed,0x3e71befb,0x3ee23dc8,0x3e153ed5,0xbef53e8e,
0xbe443f00,0xbeed0000,0x3e44bf00,0x3eed0000,0x3eedbeb5,0x3e443eb5,0xbeed3eb5,0xbe44beb5,0xbeed0000,0x3e44bf00,0x3eed0000,0xbe443f00,0x3e443eb5,0xbeed3eb5,0xbe44beb5,0x3eedbeb5,
0xbee20000,0x3e71bf00,0x3e153eb5,0xbef53eb5,0x3d493ed5,0xbeff3e8e,0x3ea2befb,0x3ec63dc8,0x3ec6beed,0x3ea23e44,0xbeff3e44,0x3d49beed,0xbef53dc8,0x3e15befb,0x3e713e8e,0xbee23ed5,
0x3e8ebf00,0x3ed50000,0xbed50000,0x3e8ebf00,0xbefb3e44,0x3dc8beed,0xbdc83eed,0xbefb3e44,0x3dc83eb5,0xbefb3eb5,0x3efbbeb5,0x3dc83eb5,0x3ed5beed,0x3e8e3e44,0xbe8ebe44,0x3ed5beed,
0x3ec60000,0xbea23f00,0x3effbeb5,0x3d493eb5,0x3e71befb,0x3ee2bdc8,0xbe15be8e,0x3ef5bed5,0xbef53e44,0x3e15beed,0xbee23eed,0xbe71be44,0xbd493ed5,0xbeff3e8e,0x3ea23dc8,0xbec63efb,
0x3eb53f00,0xbeb50000,0x3eb53f00,0xbeb50000,0xbeb50000,0xbeb5bf00,0xbeb50000,0xbeb5bf00,0xbeb5bf00,0x3eb50000,0xbeb5bf00,0x3eb50000,0x3eb50000,0x3eb53f00,0x3eb50000,0x3eb53f00,
0x3d490000,0x3effbf00,0x3ec6beb5,0x3ea2beb5,0x3e15bdc8,0x3ef5befb,0x3ee2bed5,0x3e71be8e,0x3e71be44,0x3ee2beed,0x3ef5beed,0x3e15be44,0x3ea2be8e,0x3ec6bed5,0x3effbefb,0x3d49bdc8,
0x3efbbf00,0xbdc80000,0xbdc80000,0xbefb3f00,0x3ed5beed,0xbe8e3e44,0xbe8e3e44,0xbed53eed,0x3e8ebeb5,0xbed53eb5,0xbed53eb5,0xbe8e3eb5,0x3dc8be44,0xbefb3eed,0xbefb3eed,0xbdc83e44,
0xbe150000,0xbef53f00,0xbe713eb5,0x3ee2beb5,0xbec63e8e,0xbea23ed5,0x3d493dc8,0x3effbefb,0xbeff3eed,0xbd493e44,0x3ea2be44,0x3ec6beed,0xbee23efb,0x3e71bdc8,0x3ef5bed5,0x3e15be8e,
0xbeed3f00,0x3e440000,0x3eedbf00,0xbe440000,0xbe443eb5,0x3eedbeb5,0x3e44beb5,0xbeed3eb5,0x3e440000,0x3eedbf00,0xbe440000,0xbeed3f00,0x3eedbeb5,0x3e44beb5,0xbeed3eb5,0xbe443eb5,
0x3e710000,0x3ee2bf00,0xbef53eb5,0xbe153eb5,0x3effbed5,0x3d49be8e,0xbec63efb,0x3ea2bdc8,0x3ea2beed,0xbec63e44,0x3d493e44,0x3effbeed,0xbe15bdc8,0xbef53efb,0x3ee2be8e,0x3e71bed5,
0x3ed5bf00,0xbe8e0000,0x3e8e0000,0x3ed5bf00,0xbdc8be44,0xbefb3eed,0x3efbbeed,0xbdc8be44,0xbefb3eb5,0xbdc83eb5,0x3dc8beb5,0xbefb3eb5,0xbe8e3eed,0x3ed5be44,0xbed53e44,0xbe8e3eed,
0xbea20000,0xbec63f00,0x3d49beb5,0xbeff3eb5,0xbee23efb,0x3e713dc8,0xbef53e8e,0xbe153ed5,0x3e153e44,0x3ef5beed,0xbe713eed,0x3ee2be44,0x3effbed5,0xbd49be8e,0x3ec6bdc8,0x3ea2befb,
0xbeb53f00,0xbeb50000,0xbeb53f00,0xbeb50000,0x3eb50000,0xbeb53f00,0x3eb50000,0xbeb53f00,0x3eb5bf00,0x3eb50000,0x3eb5bf00,0x3eb50000,0xbeb50000,0x3eb5bf00,0xbeb50000,0x3eb5bf00,
0x3eff0000,0xbd49bf00,0x3ea2beb5,0xbec6beb5,0xbef53dc8,0x3e153efb,0xbe713ed5,0x3ee23e8e,0x3ee2be44,0xbe71beed,0x3e15beed,0xbef5be44,0xbec63e8e,0x3ea23ed5,0xbd493efb,0x3eff3dc8,
0xbdc8bf00,0xbefb0000,0xbefb0000,0x3dc83f00,0x3e8e3eed,0x3ed5be44,0x3ed5be44,0xbe8ebeed,0xbed5beb5,0xbe8e3eb5,0xbe8e3eb5,0x3ed53eb5,0x3efb3e44,0x3dc8beed,0x3dc8beed,0xbefbbe44,
0xbef50000,0x3e153f00,0x3ee23eb5,0x3e71beb5,0x3ea2be8e,0xbec6bed5,0xbeffbdc8,0x3d493efb,0xbd493eed,0x3eff3e44,0x3ec6be44,0xbea2beed,0xbe71befb,0xbee23dc8,0xbe153ed5,0x3ef53e8e,
0x3e443f00,0x3eed0000,0xbe44bf00,0xbeed0000,0xbeedbeb5,0xbe443eb5,0x3eed3eb5,0x3e44beb5,0x3eed0000,0xbe44bf00,0xbeed0000,0x3e443f00,0xbe443eb5,0x3eed3eb5,0x3e44beb5,0xbeedbeb5,
0x3ee20000,0xbe71bf00,0xbe153eb5,0x3ef53eb5,0xbd493ed5,0x3eff3e8e,0xbea2befb,0xbec63dc8,0xbec6beed,0xbea23e44,0x3eff3e44,0xbd49beed,0x3ef53dc8,0xbe15befb,0xbe713e8e,0x3ee23ed5,
0xbe8ebf00,0xbed50000,0x3ed50000,0xbe8ebf00,0x3efb3e44,0xbdc8beed,0x3dc83eed,0x3efb3e44,0xbdc83eb5,0x3efb3eb5,0xbefbbeb5,0xbdc83eb5,0xbed5beed,0xbe8e3e44,0x3e8ebe44,0xbed5beed,
0xbec60000,0x3ea23f00,0xbeffbeb5,0xbd493eb5,0xbe71befb,0xbee2bdc8,0x3e15be8e,0xbef5bed5,0x3ef53e44,0xbe15beed,0x3ee23eed,0x3e71be44,0x3d493ed5,0x3eff3e8e,0xbea23dc8,0x3ec63efb,
0x3f003f00,0xbf003f00,0x3f003f00,0xbf003f00,0x3f003f00,0xbf003f00,0x3f003f00,0xbf003f00,0x3f003f00,0xbf003f00,0x3f003f00,0xbf003f00,0x3f003f00,0xbf003f00,0x3f003f00,0xbf003f00,
0xbeffbf00,0x3d490000,0xbea2beb5,0x3ec63eb5,0xbef5befb,0x3e153dc8,0xbe71be8e,0x3ee23ed5,0xbee2beed,0x3e713e44,0xbe15be44,0x3ef53eed,0xbec6bed5,0x3ea23e8e,0xbd49bdc8,0x3eff3efb,
0x3efb3f00,0xbdc80000,0xbdc80000,0xbefbbf00,0x3ed53eed,0xbe8ebe44,0xbe8ebe44,0xbed5beed,0x3e8e3eb5,0xbed5beb5,0xbed5beb5,0xbe8ebeb5,0x3dc83e44,0xbefbbeed,0xbefbbeed,0xbdc8be44,
0xbef5bf00,0x3e150000,0x3ee23eb5,0x3e713eb5,0xbea2bed5,0x3ec63e8e,0x3eff3efb,0xbd493dc8,0xbd49be44,0x3eff3eed,0x3ec63eed,0xbea2be44,0x3e713dc8,0x3ee23efb,0x3e153e8e,0xbef5bed5,
0x3eed3f00,0xbe440000,0xbeedbf00,0x3e440000,0x3e443eb5,0xbeedbeb5,0xbe44beb5,0x3eed3eb5,0xbe440000,0xbeedbf00,0x3e440000,0x3eed3f00,0xbeedbeb5,0xbe44beb5,0x3eed3eb5,0x3e443eb5,
0xbee2bf00,0x3e710000,0x3e153eb5,0xbef5beb5,0xbd49be8e,0x3eff3ed5,0xbea2bdc8,0xbec6befb,0x3ec63e44,0x3ea23eed,0xbeffbeed,0x3d49be44,0x3ef53efb,0xbe153dc8,0xbe71bed5,0x3ee23e8e,
0x3ed53f00,0xbe8e0000,0x3e8e0000,0x3ed53f00,0xbdc83e44,0xbefbbeed,0x3efb3eed,0xbdc83e44,0xbefbbeb5,0xbdc8beb5,0x3dc83eb5,0xbefbbeb5,0xbe8ebeed,0x3ed53e44,0xbed5be44,0xbe8ebeed,
0xbec6bf00,0x3ea20000,0xbeffbeb5,0xbd49beb5,0x3e71bdc8,0x3ee23efb,0xbe15bed5,0x3ef53e8e,0x3ef53eed,0xbe153e44,0x3ee23e44,0x3e713eed,0xbd493e8e,0xbeffbed5,0x3ea23efb,0xbec6bdc8,
0x3f00,0xbf000000,0x3f00,0xbf000000,0xbf00,0x3f000000,0xbf00,0x3f000000,0x3f00,0xbf000000,0x3f00,0xbf000000,0xbf00,0x3f000000,0xbf00,0x3f000000,
0x3d49bf00,0x3eff0000,0x3ec6beb5,0x3ea23eb5,0xbe153efb,0xbef5bdc8,0xbee23e8e,0xbe71bed5,0x3e71beed,0x3ee23e44,0x3ef5be44,0x3e153eed,0xbea23ed5,0xbec6be8e,0xbeff3dc8,0xbd49befb,
0xbdc83f00,0xbefb0000,0xbefb0000,0x3dc8bf00,0x3e8ebeed,0x3ed53e44,0x3ed53e44,0xbe8e3eed,0xbed53eb5,0xbe8ebeb5,0xbe8ebeb5,0x3ed5beb5,0x3efbbe44,0x3dc83eed,0x3dc83eed,0xbefb3e44,
0x3e15bf00,0x3ef50000,0x3e713eb5,0xbee23eb5,0xbec63ed5,0xbea2be8e,0x3d49befb,0x3effbdc8,0x3effbe44,0x3d493eed,0xbea23eed,0xbec6be44,0xbee2bdc8,0x3e71befb,0x3ef5be8e,0x3e153ed5,
0xbe443f00,0xbeed0000,0x3e44bf00,0x3eed0000,0x3eedbeb5,0x3e443eb5,0xbeed3eb5,0xbe44beb5,0xbeed0000,0x3e44bf00,0x3eed0000,0xbe443f00,0x3e443eb5,0xbeed3eb5,0xbe44beb5,0x3eedbeb5,
0x3e71bf00,0x3ee20000,0xbef53eb5,0xbe15beb5,0xbeff3e8e,0xbd49bed5,0x3ec63dc8,0xbea23efb,0x3ea23e44,0xbec63eed,0x3d49beed,0x3effbe44,0x3e15befb,0x3ef5bdc8,0xbee23ed5,0xbe71be8e,
0xbe8e3f00,0xbed50000,0x3ed50000,0xbe8e3f00,0x3efbbe44,0xbdc83eed,0x3dc8beed,0x3efbbe44,0xbdc8beb5,0x3efbbeb5,0xbefb3eb5,0xbdc8beb5,0xbed53eed,0xbe8ebe44,0x3e8e3e44,0xbed53eed,
0x3ea2bf00,0x3ec60000,0xbd49beb5,0x3effbeb5,0xbee23dc8,0x3e71befb,0xbef53ed5,0xbe15be8e,0xbe153eed,0xbef53e44,0x3e713e44,0xbee23eed,0x3effbe8e,0xbd493ed5,0x3ec6befb,0x3ea23dc8,
0x3eb53f00,0xbeb50000,0x3eb53f00,0xbeb50000,0xbeb50000,0xbeb5bf00,0xbeb50000,0xbeb5bf00,0xbeb5bf00,0x3eb50000,0xbeb5bf00,0x3eb50000,0x3eb50000,0x3eb53f00,0x3eb50000,0x3eb53f00,
0x3effbf00,0xbd490000,0x3ea2beb5,0xbec63eb5,0x3ef5befb,0xbe153dc8,0x3e71be8e,0xbee23ed5,0x3ee2beed,0xbe713e44,0x3e15be44,0xbef53eed,0x3ec6bed5,0xbea23e8e,0x3d49bdc8,0xbeff3efb,
0xbefb3f00,0x3dc80000,0x3dc80000,0x3efbbf00,0xbed53eed,0x3e8ebe44,0x3e8ebe44,0x3ed5beed,0xbe8e3eb5,0x3ed5beb5,0x3ed5beb5,0x3e8ebeb5,0xbdc83e44,0x3efbbeed,0x3efbbeed,0x3dc8be44,
0x3ef5bf00,0xbe150000,0xbee23eb5,0xbe713eb5,0x3ea2bed5,0xbec63e8e,0xbeff3efb,0x3d493dc8,0x3d49be44,0xbeff3eed,0xbec63eed,0x3ea2be44,0xbe713dc8,0xbee23efb,0xbe153e8e,0x3ef5bed5,
0xbeed3f00,0x3e440000,0x3eedbf00,0xbe440000,0xbe443eb5,0x3eedbeb5,0x3e44beb5,0xbeed3eb5,0x3e440000,0x3eedbf00,0xbe440000,0xbeed3f00,0x3eedbeb5,0x3e44beb5,0xbeed3eb5,0xbe443eb5,
0x3ee2bf00,0xbe710000,0xbe153eb5,0x3ef5beb5,0x3d49be8e,0xbeff3ed5,0x3ea2bdc8,0x3ec6befb,0xbec63e44,0xbea23eed,0x3effbeed,0xbd49be44,0xbef53efb,0x3e153dc8,0x3e71bed5,0xbee23e8e,
0xbed53f00,0x3e8e0000,0xbe8e0000,0xbed53f00,0x3dc83e44,0x3efbbeed,0xbefb3eed,0x3dc83e44,0x3efbbeb5,0x3dc8beb5,0xbdc83eb5,0x3efbbeb5,0x3e8ebeed,0xbed53e44,0x3ed5be44,0x3e8ebeed,
0x3ec6bf00,0xbea20000,0x3effbeb5,0x3d49beb5,0xbe71bdc8,0xbee23efb,0x3e15bed5,0xbef53e8e,0xbef53eed,0x3e153e44,0xbee23e44,0xbe713eed,0x3d493e8e,0x3effbed5,0xbea23efb,0x3ec6bdc8,
0xbeb53f00,0xbeb50000,0xbeb53f00,0xbeb50000,0x3eb50000,0xbeb53f00,0x3eb50000,0xbeb53f00,0x3eb5bf00,0x3eb50000,0x3eb5bf00,0x3eb50000,0xbeb50000,0x3eb5bf00,0xbeb50000,0x3eb5bf00,
0xbd49bf00,0xbeff0000,0xbec6beb5,0xbea23eb5,0x3e153efb,0x3ef5bdc8,0x3ee23e8e,0x3e71bed5,0xbe71beed,0xbee23e44,0xbef5be44,0xbe153eed,0x3ea23ed5,0x3ec6be8e,0x3eff3dc8,0x3d49befb,
0x3dc83f00,0x3efb0000,0x3efb0000,0xbdc8bf00,0xbe8ebeed,0xbed53e44,0xbed53e44,0x3e8e3eed,0x3ed53eb5,0x3e8ebeb5,0x3e8ebeb5,0xbed5beb5,0xbefbbe44,0xbdc83eed,0xbdc83eed,0x3efb3e44,
0xbe15bf00,0xbef50000,0xbe713eb5,0x3ee23eb5,0x3ec63ed5,0x3ea2be8e,0xbd49befb,0xbeffbdc8,0xbeffbe44,0xbd493eed,0x3ea23eed,0x3ec6be44,0x3ee2bdc8,0xbe71befb,0xbef5be8e,0xbe153ed5,
0x3e443f00,0x3eed0000,0xbe44bf00,0xbeed0000,0xbeedbeb5,0xbe443eb5,0x3eed3eb5,0x3e44beb5,0x3eed0000,0xbe44bf00,0xbeed0000,0x3e443f00,0xbe443eb5,0x3eed3eb5,0x3e44beb5,0xbeedbeb5,
0xbe71bf00,0xbee20000,0x3ef53eb5,0x3e15beb5,0x3eff3e8e,0x3d49bed5,0xbec63dc8,0x3ea23efb,0xbea23e44,0x3ec63eed,0xbd49beed,0xbeffbe44,0xbe15befb,0xbef5bdc8,0x3ee23ed5,0x3e71be8e,
0x3e8e3f00,0x3ed50000,0xbed50000,0x3e8e3f00,0xbefbbe44,0x3dc83eed,0xbdc8beed,0xbefbbe44,0x3dc8beb5,0xbefbbeb5,0x3efb3eb5,0x3dc8beb5,0x3ed53eed,0x3e8ebe44,0xbe8e3e44,0x3ed53eed,
0xbea2bf00,0xbec60000,0x3d49beb5,0xbeffbeb5,0x3ee23dc8,0xbe71befb,0x3ef53ed5,0x3e15be8e,0x3e153eed,0x3ef53e44,0xbe713e44,0x3ee23eed,0xbeffbe8e,0x3d493ed5,0xbec6befb,0xbea23dc8,
0x3f003f00,0xbf003f00,0x3f003f00,0xbf003f00,0x3f003f00,0xbf003f00,0x3f003f00,0xbf003f00,0x3f003f00,0xbf003f00,0x3f003f00,0xbf003f00,0x3f003f00,0xbf003f00,0x3f003f00,0xbf003f00,
0x3d490000,0x3eff3f00,0x3ec63eb5,0x3ea23eb5,0x3e153dc8,0x3ef53efb,0x3ee23ed5,0x3e713e8e,0x3e713e44,0x3ee23eed,0x3ef53eed,0x3e153e44,0x3ea23e8e,0x3ec63ed5,0x3eff3efb,0x3d493dc8,
0xbefbbf00,0x3dc80000,0x3dc80000,0x3efb3f00,0xbed5beed,0x3e8e3e44,0x3e8e3e44,0x3ed53eed,0xbe8ebeb5,0x3ed53eb5,0x3ed53eb5,0x3e8e3eb5,0xbdc8be44,0x3efb3eed,0x3efb3eed,0x3dc83e44,
0xbe150000,0xbef5bf00,0xbe71beb5,0x3ee23eb5,0xbec6be8e,0xbea2bed5,0x3d49bdc8,0x3eff3efb,0xbeffbeed,0xbd49be44,0x3ea23e44,0x3ec63eed,0xbee2befb,0x3e713dc8,0x3ef53ed5,0x3e153e8e,
0x3eed3f00,0xbe440000,0xbeedbf00,0x3e440000,0x3e443eb5,0xbeedbeb5,0xbe44beb5,0x3eed3eb5,0xbe440000,0xbeedbf00,0x3e440000,0x3eed3f00,0xbeedbeb5,0xbe44beb5,0x3eed3eb5,0x3e443eb5,
0x3e710000,0x3ee23f00,0xbef5beb5,0xbe15beb5,0x3eff3ed5,0x3d493e8e,0xbec6befb,0x3ea23dc8,0x3ea23eed,0xbec6be44,0x3d49be44,0x3eff3eed,0xbe153dc8,0xbef5befb,0x3ee23e8e,0x3e713ed5,
0xbed5bf00,0x3e8e0000,0xbe8e0000,0xbed5bf00,0x3dc8be44,0x3efb3eed,0xbefbbeed,0x3dc8be44,0x3efb3eb5,0x3dc83eb5,0xbdc8beb5,0x3efb3eb5,0x3e8e3eed,0xbed5be44,0x3ed53e44,0x3e8e3eed,
0xbea20000,0xbec6bf00,0x3d493eb5,0xbeffbeb5,0xbee2befb,0x3e71bdc8,0xbef5be8e,0xbe15bed5,0x3e15be44,0x3ef53eed,0xbe71beed,0x3ee23e44,0x3eff3ed5,0xbd493e8e,0x3ec63dc8,0x3ea23efb,
0x3f00,0xbf000000,0x3f00,0xbf000000,0xbf00,0x3f000000,0xbf00,0x3f000000,0x3f00,0xbf000000,0x3f00,0xbf000000,0xbf00,0x3f000000,0xbf00,0x3f000000,
0x3eff0000,0xbd493f00,0x3ea23eb5,0xbec63eb5,0xbef5bdc8,0x3e15befb,0xbe71bed5,0x3ee2be8e,0x3ee23e44,0xbe713eed,0x3e153eed,0xbef53e44,0xbec6be8e,0x3ea2bed5,0xbd49befb,0x3effbdc8,
0x3dc8bf00,0x3efb0000,0x3efb0000,0xbdc83f00,0xbe8e3eed,0xbed5be44,0xbed5be44,0x3e8ebeed,0x3ed5beb5,0x3e8e3eb5,0x3e8e3eb5,0xbed53eb5,0xbefb3e44,0xbdc8beed,0xbdc8beed,0x3efbbe44,
0xbef50000,0x3e15bf00,0x3ee2beb5,0x3e713eb5,0x3ea23e8e,0xbec63ed5,0xbeff3dc8,0x3d49befb,0xbd49beed,0x3effbe44,0x3ec63e44,0xbea23eed,0xbe713efb,0xbee2bdc8,0xbe15bed5,0x3ef5be8e,
0xbe443f00,0xbeed0000,0x3e44bf00,0x3eed0000,0x3eedbeb5,0x3e443eb5,0xbeed3eb5,0xbe44beb5,0xbeed0000,0x3e44bf00,0x3eed0000,0xbe443f00,0x3e443eb5,0xbeed3eb5,0xbe44beb5,0x3eedbeb5,
0x3ee20000,0xbe713f00,0xbe15beb5,0x3ef5beb5,0xbd49bed5,0x3effbe8e,0xbea23efb,0xbec6bdc8,0xbec63eed,0xbea2be44,0x3effbe44,0xbd493eed,0x3ef5bdc8,0xbe153efb,0xbe71be8e,0x3ee2bed5,
0x3e8ebf00,0x3ed50000,0xbed50000,0x3e8ebf00,0xbefb3e44,0x3dc8beed,0xbdc83eed,0xbefb3e44,0x3dc83eb5,0xbefb3eb5,0x3efbbeb5,0x3dc83eb5,0x3ed5beed,0x3e8e3e44,0xbe8ebe44,0x3ed5beed,
0xbec60000,0x3ea2bf00,0xbeff3eb5,0xbd49beb5,0xbe713efb,0xbee23dc8,0x3e153e8e,0xbef53ed5,0x3ef5be44,0xbe153eed,0x3ee2beed,0x3e713e44,0x3d49bed5,0x3effbe8e,0xbea2bdc8,0x3ec6befb,
0x3eb53f00,0xbeb50000,0x3eb53f00,0xbeb50000,0xbeb50000,0xbeb5bf00,0xbeb50000,0xbeb5bf00,0xbeb5bf00,0x3eb50000,0xbeb5bf00,0x3eb50000,0x3eb50000,0x3eb53f00,0x3eb50000,0x3eb53f00,
0xbd490000,0xbeff3f00,0xbec63eb5,0xbea23eb5,0xbe153dc8,0xbef53efb,0xbee23ed5,0xbe713e8e,0xbe713e44,0xbee23eed,0xbef53eed,0xbe153e44,0xbea23e8e,0xbec63ed5,0xbeff3efb,0xbd493dc8,
0x3efbbf00,0xbdc80000,0xbdc80000,0xbefb3f00,0x3ed5beed,0xbe8e3e44,0xbe8e3e44,0xbed53eed,0x3e8ebeb5,0xbed53eb5,0xbed53eb5,0xbe8e3eb5,0x3dc8be44,0xbefb3eed,0xbefb3eed,0xbdc83e44,
0x3e150000,0x3ef5bf00,0x3e71beb5,0xbee23eb5,0x3ec6be8e,0x3ea2bed5,0xbd49bdc8,0xbeff3efb,0x3effbeed,0x3d49be44,0xbea23e44,0xbec63eed,0x3ee2befb,0xbe713dc8,0xbef53ed5,0xbe153e8e,
0xbeed3f00,0x3e440000,0x3eedbf00,0xbe440000,0xbe443eb5,0x3eedbeb5,0x3e44beb5,0xbeed3eb5,0x3e440000,0x3eedbf00,0xbe440000,0xbeed3f00,0x3eedbeb5,0x3e44beb5,0xbeed3eb5,0xbe443eb5,
0xbe710000,0xbee23f00,0x3ef5beb5,0x3e15beb5,0xbeff3ed5,0xbd493e8e,0x3ec6befb,0xbea23dc8,0xbea23eed,0x3ec6be44,0xbd49be44,0xbeff3eed,0x3e153dc8,0x3ef5befb,0xbee23e8e,0xbe713ed5,
0x3ed5bf00,0xbe8e0000,0x3e8e0000,0x3ed5bf00,0xbdc8be44,0xbefb3eed,0x3efbbeed,0xbdc8be44,0xbefb3eb5,0xbdc83eb5,0x3dc8beb5,0xbefb3eb5,0xbe8e3eed,0x3ed5be44,0xbed53e44,0xbe8e3eed,
0x3ea20000,0x3ec6bf00,0xbd493eb5,0x3effbeb5,0x3ee2befb,0xbe71bdc8,0x3ef5be8e,0x3e15bed5,0xbe15be44,0xbef53eed,0x3e71beed,0xbee23e44,0xbeff3ed5,0x3d493e8e,0xbec63dc8,0xbea23efb,
0xbeb53f00,0xbeb50000,0xbeb53f00,0xbeb50000,0x3eb50000,0xbeb53f00,0x3eb50000,0xbeb53f00,0x3eb5bf00,0x3eb50000,0x3eb5bf00,0x3eb50000,0xbeb50000,0x3eb5bf00,0xbeb50000,0x3eb5bf00,
0xbeff0000,0x3d493f00,0xbea23eb5,0x3ec63eb5,0x3ef5bdc8,0xbe15befb,0x3e71bed5,0xbee2be8e,0xbee23e44,0x3e713eed,0xbe153eed,0x3ef53e44,0x3ec6be8e,0xbea2bed5,0x3d49befb,0xbeffbdc8,
0xbdc8bf00,0xbefb0000,0xbefb0000,0x3dc83f00,0x3e8e3eed,0x3ed5be44,0x3ed5be44,0xbe8ebeed,0xbed5beb5,0xbe8e3eb5,0xbe8e3eb5,0x3ed53eb5,0x3efb3e44,0x3dc8beed,0x3dc8beed,0xbefbbe44,
0x3ef50000,0xbe15bf00,0xbee2beb5,0xbe713eb5,0xbea23e8e,0x3ec63ed5,0x3eff3dc8,0xbd49befb,0x3d49beed,0xbeffbe44,0xbec63e44,0x3ea23eed,0x3e713efb,0x3ee2bdc8,0x3e15bed5,0xbef5be8e,
0x3e443f00,0x3eed0000,0xbe44bf00,0xbeed0000,0xbeedbeb5,0xbe443eb5,0x3eed3eb5,0x3e44beb5,0x3eed0000,0xbe44bf00,0xbeed0000,0x3e443f00,0xbe443eb5,0x3eed3eb5,0x3e44beb5,0xbeedbeb5,
0xbee20000,0x3e713f00,0x3e15beb5,0xbef5beb5,0x3d49bed5,0xbeffbe8e,0x3ea23efb,0x3ec6bdc8,0x3ec63eed,0x3ea2be44,0xbeffbe44,0x3d493eed,0xbef5bdc8,0x3e153efb,0x3e71be8e,0xbee2bed5,
0xbe8ebf00,0xbed50000,0x3ed50000,0xbe8ebf00,0x3efb3e44,0xbdc8beed,0x3dc83eed,0x3efb3e44,0xbdc83eb5,0x3efb3eb5,0xbefbbeb5,0xbdc83eb5,0xbed5beed,0xbe8e3e44,0x3e8ebe44,0xbed5beed,
0x3ec60000,0xbea2bf00,0x3eff3eb5,0x3d49beb5,0x3e713efb,0x3ee23dc8,0xbe153e8e,0x3ef53ed5,0xbef5be44,0x3e153eed,0xbee2beed,0xbe713e44,0xbd49bed5,0xbeffbe8e,0x3ea2bdc8,0xbec6befb,
0x3f800000,0x0,0x3f800000,0x0,0x3f800000,0x0,0x3f800000,0x0,0x3f800000,0x0,0x3f800000,0x0,0x3f800000,0x0,0x3f800000,0x0,
0x3f800000,0x0,0x3f7fec43,0xbcc90ab0,0x3f7fb10f,0xbd48fb30,0x3f7f4e6d,0xbd96a905,0x3f7ec46d,0xbdc8bd36,0x3f7e1324,0xbdfab273,0x3f7d3aac,0xbe164083,0x3f7c3b28,0xbe2f10a2,
0x3f800000,0x0,0x3f7ffec4,0xbbc90f88,0x3f7ffb11,0xbc490e90,0x3f7ff4e6,0xbc96c9b6,0x3f7fec43,0xbcc90ab0,0x3f7fe129,0xbcfb49ba,0x3f7fd397,0xbd16c32c,0x3f7fc38f,0xbd2fe007,
0x3f800000,0x0,0x3f7fe129,0xbcfb49ba,0x3f7f84ab,0xbd7b2b74,0x3f7eea9d,0xbdbc3ac3,0x3f7e1324,0xbdfab273,0x3f7cfe73,0xbe1c76de,0x3f7baccd,0xbe3b6ecf,0x3f7a1e84,0xbe5a3997,
0x3f800000,0x0,0x3f7ffb11,0xbc490e90,0x3f7fec43,0xbcc90ab0,0x3f7fd397,0xbd16c32c,0x3f7fb10f,0xbd48fb30,0x3f7f84ab,0xbd7b2b74,0x3f7f4e6d,0xbd96a905,0x3f7f0e58,0xbdafb680,
0x3f800000,0x0,0x3f7fd397,0xbd16c32c,0x3f7f4e6d,0xbd96a905,0x3f7e70b0,0xbde1bc2e,0x3f7d3aac,0xbe164083,0x3f7baccd,0xbe3b6ecf,0x3f79c79d,0xbe605c13,0x3f778bc5,0xbe827dc0,
0x3f800000,0x0,0x3f7ff4e6,0xbc96c9b6,0x3f7fd397,0xbd16c32c,0x3f7f9c18,0xbd621469,0x3f7f4e6d,0xbd96a905,0x3f7eea9d,0xbdbc3ac3,0x3f7e70b0,0xbde1bc2e,0x3f7de0b1,0xbe039502,
0x3f800000,0x0,0x3f7fc38f,0xbd2fe007,0x3f7f0e58,0xbdafb680,0x3f7de0b1,0xbe039502,0x3f7c3b28,0xbe2f10a2,0x3f7a1e84,0xbe5a3997,0x3f778bc5,0xbe827dc0,0x3f748422,0xbe97a117,
0x3f800000,0x0,0x3f7fb10f,0xbd48fb30,0x3f7ec46d,0xbdc8bd36,0x3f7d3aac,0xbe164083,0x3f7b14be,0xbe47c5c2,0x3f7853f8,0xbe78cfcc,0x3f74fa0b,0xbe94a031,0x3f710908,0xbeac7cd4,
0x3f800000,0x0,0x3f7f4e6d,0xbd96a905,0x3f7d3aac,0xbe164083,0x3f79c79d,0xbe605c13,0x3f74fa0b,0xbe94a031,0x3f6ed89e,0xbeb8442a,0x3f676bd8,0xbedae880,0x3f5ebe05,0xbefc5d27,
0x3f800000,0x0,0x3f7f9c18,0xbd621469,0x3f7e70b0,0xbde1bc2e,0x3f7c7eb0,0xbe28defc,0x3f79c79d,0xbe605c13,0x3f764d97,0xbe8b9507,0x3f721352,0xbea68f12,0x3f6d1c1d,0xbec1071e,
0x3f800000,0x0,0x3f7f2f9d,0xbda3308c,0x3f7cbfc9,0xbe22abb6,0x3f78b47b,0xbe72b651,0x3f731447,0xbea09ae5,0x3f6be858,0xbec6d529,0x3f633c5a,0xbeebcbbb,0x3f591e6a,0xbf07a136,
0x3f800000,0x0,0x3f7f84ab,0xbd7b2b74,0x3f7e1324,0xbdfab273,0x3f7baccd,0xbe3b6ecf,0x3f7853f8,0xbe78cfcc,0x3f740bdd,0xbe9aa086,0x3f6ed89e,0xbeb8442a,0x3f68bf3c,0xbed53641,
0x3f800000,0x0,0x3f7f0e58,0xbdafb680,0x3f7c3b28,0xbe2f10a2,0x3f778bc5,0xbe827dc0,0x3f710908,0xbeac7cd4,0x3f68bf3c,0xbed53641,0x3f5ebe05,0xbefc5d27,0x3f531849,0xbf10d3cd,
0x3f800000,0x0,0x3f7f6ac7,0xbd8a200a,0x3f7dabcc,0xbe09cf86,0x3f7ac516,0xbe4dee60,0x3f76ba07,0xbe888e93,0x3f718f57,0xbea986c4,0x3f6b4b0c,0xbec9b953,0x3f63f473,0xbee900b7,
0x3f800000,0x0,0x3f7eea9d,0xbdbc3ac3,0x3f7baccd,0xbe3b6ecf,0x3f764d97,0xbe8b9507,0x3f6ed89e,0xbeb8442a,0x3f655e0b,0xbee363fa,0x3f59f26a,0xbf064b82,0x3f4cae79,0xbf19c200,
0x3f800000,0x0,0x3f7ec46d,0xbdc8bd36,0x3f7b14be,0xbe47c5c2,0x3f74fa0b,0xbe94a031,0x3f6c835e,0xbec3ef15,0x3f61c598,0xbef15aea,0x3f54db31,0xbf0e39da,0x3f45e403,0xbf226799,
0x3f800000,0x0,0x3f7e1324,0xbdfab273,0x3f7853f8,0xbe78cfcc,0x3f6ed89e,0xbeb8442a,0x3f61c598,0xbef15aea,0x3f514d3d,0xbf13682a,0x3f3daef9,0xbf2beb4a,0x3f273656,0xbf41d870,
0x3f800000,0x0,0x3f7e9bc9,0xbdd53db9,0x3f7a7302,0xbe541501,0x3f73913f,0xbe9d9e78,0x3f6a09a7,0xbecf7bca,0x3f5df6be,0xbeff17b2,0x3f4f7a1f,0xbf15f6d9,0x3f3ebc1b,0xbf2ac082,
0x3f800000,0x0,0x3f7de0b1,0xbe039502,0x3f778bc5,0xbe827dc0,0x3f6d1c1d,0xbec1071e,0x3f5ebe05,0xbefc5d27,0x3f4cae79,0xbf19c200,0x3f373a23,0xbf32c8c9,0x3f1ebc12,0xbf48d8b3,
0x3f800000,0x0,0x3f7e70b0,0xbde1bc2e,0x3f79c79d,0xbe605c13,0x3f721352,0xbea68f12,0x3f676bd8,0xbedae880,0x3f59f26a,0xbf064b82,0x3f49d112,0xbf1d7fd1,0x3f373a23,0xbf32c8c9,
0x3f800000,0x0,0x3f7dabcc,0xbe09cf86,0x3f76ba07,0xbe888e93,0x3f6b4b0c,0xbec9b953,0x3f5b941a,0xbf039c3d,0x3f47de65,0xbf1ff6cb,0x3f3085bb,0xbf396842,0x3f15f6d9,0xbf4f7a1f,
0x3f800000,0x0,0x3f7e4323,0xbdee3876,0x3f791298,0xbe6c9a7f,0x3f708066,0xbeaf713a,0x3f64aa59,0xbee63375,0x3f55b993,0xbf0cead0,0x3f43e200,0xbf24d225,0x3f2f61a5,0xbf3a7ca4,
0x3f800000,0x0,0x3f7d7474,0xbe1008b7,0x3f75dec6,0xbe8e9a22,0x3f696591,0xbed25a09,0x3f584853,0xbf08f59b,0x3f42de29,0xbf26050a,0x3f299415,0xbf3fc767,0x3f0cead0,0xbf55b993,
0x3f800000,0x0,0x3f7d3aac,0xbe164083,0x3f74fa0b,0xbe94a031,0x3f676bd8,0xbedae880,0x3f54db31,0xbf0e39da,0x3f3daef9,0xbf2beb4a,0x3f226799,0xbf45e403,0x3f039c3d,0xbf5b941a,
0x3f800000,0x0,0x3f7c3b28,0xbe2f10a2,0x3f710908,0xbeac7cd4,0x3f5ebe05,0xbefc5d27,0x3f45e403,0xbf226799,0x3f273656,0xbf41d870,0x3f039c3d,0xbf5b941a,0x3eb8442a,0xbf6ed89e,
0x3f800000,0x0,0x3f7cfe73,0xbe1c76de,0x3f740bdd,0xbe9aa086,0x3f655e0b,0xbee363fa,0x3f514d3d,0xbf13682a,0x3f385216,0xbf31a81d,0x3f1b02c6,0xbf4bbbf8,0x3ef41f07,0xbf6106f2,
0x3f800000,0x0,0x3f7bf531,0xbe354098,0x3f6ff573,0xbeb263ef,0x3f5c61c7,0xbf0242b1,0x3f41d870,0xbf273656,0x3f212ff9,0xbf46e22a,0x3ef6e0cb,0xbf604621,0x3ea395c5,0xbf7294f8,
0x3f800000,0x0,0x3f7cbfc9,0xbe22abb6,0x3f731447,0xbea09ae5,0x3f633c5a,0xbeebcbbb,0x3f4d9f02,0xbf187fc0,0x3f32c8c9,0xbf373a23,0x3f13682a,0xbf514d3d,0x3ee0924f,0xbf660f88,
0x3f800000,0x0,0x3f7baccd,0xbe3b6ecf,0x3f6ed89e,0xbeb8442a,0x3f59f26a,0xbf064b82,0x3f3daef9,0xbf2beb4a,0x3f1b02c6,0xbf4bbbf8,0x3ee63375,0xbf64aa59,0x3e8e9a22,0xbf75dec6,
0x3f800000,0x0,0x3f7c7eb0,0xbe28defc,0x3f721352,0xbea68f12,0x3f6106f2,0xbef41f07,0x3f49d112,0xbf1d7fd1,0x3f2d1469,0xbf3ca003,0x3f0b9a6b,0xbf5695e5,0x3ecc9b8b,0xbf6aab7b,
0x3f800000,0x0,0x3f7b61fc,0xbe419b37,0x3f6db293,0xbebe1d4a,0x3f577026,0xbf0a48ad,0x3f396842,0xbf3085bb,0x3f14b039,0xbf5064af,0x3ed53641,0xbf68bf3c,0x3e72b651,0xbf78b47b,
0x3f800000,0x0,0x3f800000,0x0,0x3f800000,0x0,0x3f800000,0x0,0x3f800000,0x0,0x3f800000,0x0,0x3f800000,0x0,0x3f800000,0x0,
0x3f7b14be,0xbe47c5c2,0x3f79c79d,0xbe605c13,0x3f7853f8,0xbe78cfcc,0x3f76ba07,0xbe888e93,0x3f74fa0b,0xbe94a031,0x3f731447,0xbea09ae5,0x3f710908,0xbeac7cd4,0x3f6ed89e,0xbeb8442a,
0x3f7fb10f,0xbd48fb30,0x3f7f9c18,0xbd621469,0x3f7f84ab,0xbd7b2b74,0x3f7f6ac7,0xbd8a200a,0x3f7f4e6d,0xbd96a905,0x3f7f2f9d,0xbda3308c,0x3f7f0e58,0xbdafb680,0x3f7eea9d,0xbdbc3ac3,
0x3f7853f8,0xbe78cfcc,0x3f764d97,0xbe8b9507,0x3f740bdd,0xbe9aa086,0x3f718f57,0xbea986c4,0x3f6ed89e,0xbeb8442a,0x3f6be858,0xbec6d529,0x3f68bf3c,0xbed53641,0x3f655e0b,0xbee363fa,
0x3f7ec46d,0xbdc8bd36,0x3f7e70b0,0xbde1bc2e,0x3f7e1324,0xbdfab273,0x3f7dabcc,0xbe09cf86,0x3f7d3aac,0xbe164083,0x3f7cbfc9,0xbe22abb6,0x3f7c3b28,0xbe2f10a2,0x3f7baccd,0xbe3b6ecf,
0x3f74fa0b,0xbe94a031,0x3f721352,0xbea68f12,0x3f6ed89e,0xbeb8442a,0x3f6b4b0c,0xbec9b953,0x3f676bd8,0xbedae880,0x3f633c5a,0xbeebcbbb,0x3f5ebe05,0xbefc5d27,0x3f59f26a,0xbf064b82,
0x3f7d3aac,0xbe164083,0x3f7c7eb0,0xbe28defc,0x3f7baccd,0xbe3b6ecf,0x3f7ac516,0xbe4dee60,0x3f79c79d,0xbe605c13,0x3f78b47b,0xbe72b651,0x3f778bc5,0xbe827dc0,0x3f764d97,0xbe8b9507,
0x3f710908,0xbeac7cd4,0x3f6d1c1d,0xbec1071e,0x3f68bf3c,0xbed53641,0x3f63f473,0xbee900b7,0x3f5ebe05,0xbefc5d27,0x3f591e6a,0xbf07a136,0x3f531849,0xbf10d3cd,0x3f4cae79,0xbf19c200,
0x3f6c835e,0xbec3ef15,0x3f676bd8,0xbedae880,0x3f61c598,0xbef15aea,0x3f5b941a,0xbf039c3d,0x3f54db31,0xbf0e39da,0x3f4d9f02,0xbf187fc0,0x3f45e403,0xbf226799,0x3f3daef9,0xbf2beb4a,
0x3f54db31,0xbf0e39da,0x3f49d112,0xbf1d7fd1,0x3f3daef9,0xbf2beb4a,0x3f3085bb,0xbf396842,0x3f226799,0xbf45e403,0x3f13682a,0xbf514d3d,0x3f039c3d,0xbf5b941a,0x3ee63375,0xbf64aa59,
0x3f676bd8,0xbedae880,0x3f6106f2,0xbef41f07,0x3f59f26a,0xbf064b82,0x3f5233c6,0xbf121eb0,0x3f49d112,0xbf1d7fd1,0x3f40d0da,0xbf286605,0x3f373a23,0xbf32c8c9,0x3f2d1469,0xbf3ca003,
0x3f4d9f02,0xbf187fc0,0x3f40d0da,0xbf286605,0x3f32c8c9,0xbf373a23,0x3f239da9,0xbf44e3f5,0x3f13682a,0xbf514d3d,0x3f0242b1,0xbf5c61c7,0x3ee0924f,0xbf660f88,0x3ebb31a0,0xbf6e46be,
0x3f61c598,0xbef15aea,0x3f59f26a,0xbf064b82,0x3f514d3d,0xbf13682a,0x3f47de65,0xbf1ff6cb,0x3f3daef9,0xbf2beb4a,0x3f32c8c9,0xbf373a23,0x3f273656,0xbf41d870,0x3f1b02c6,0xbf4bbbf8,
0x3f45e403,0xbf226799,0x3f373a23,0xbf32c8c9,0x3f273656,0xbf41d870,0x3f15f6d9,0xbf4f7a1f,0x3f039c3d,0xbf5b941a,0x3ee0924f,0xbf660f88,0x3eb8442a,0xbf6ed89e,0x3e8e9a22,0xbf75dec6,
0x3f5b941a,0xbf039c3d,0x3f5233c6,0xbf121eb0,0x3f47de65,0xbf1ff6cb,0x3f3ca003,0xbf2d1469,0x3f3085bb,0xbf396842,0x3f239da9,0xbf44e3f5,0x3f15f6d9,0xbf4f7a1f,0x3f07a136,0xbf591e6a,
0x3f3daef9,0xbf2beb4a,0x3f2d1469,0xbf3ca003,0x3f1b02c6,0xbf4bbbf8,0x3f07a136,0xbf591e6a,0x3ee63375,0xbf64aa59,0x3ebb31a0,0xbf6e46be,0x3e8e9a22,0xbf75dec6,0x3e419b37,0xbf7b61fc,
0x3f3504f3,0xbf3504f3,0x3f226799,0xbf45e403,0x3f0e39da,0xbf54db31,0x3ef15aea,0xbf61c598,0x3ec3ef15,0xbf6c835e,0x3e94a031,0xbf74fa0b,0x3e47c5c2,0xbf7b14be,0x3dc8bd36,0xbf7ec46d,
0x3f0e39da,0xbf54db31,0x3ee63375,0xbf64aa59,0x3eac7cd4,0xbf710908,0x3e605c13,0xbf79c79d,0x3dc8bd36,0xbf7ec46d,0xbcc90ab0,0xbf7fec43,0xbe164083,0xbf7d3aac,0xbe888e93,0xbf76ba07,
0x3f2beb4a,0xbf3daef9,0x3f173c07,0xbf4e8d90,0x3f00e7e4,0xbf5d2d53,0x3ed25a09,0xbf696591,0x3ea09ae5,0xbf731447,0x3e5a3997,0xbf7a1e84,0x3de1bc2e,0xbf7e70b0,0x3bc90f88,0xbf7ffec4,
0x3f039c3d,0xbf5b941a,0x3ecc9b8b,0xbf6aab7b,0x3e8e9a22,0xbf75dec6,0x3e1c76de,0xbf7cfe73,0x3cc90ab0,0xbf7fec43,0xbdd53db9,0xbf7e9bc9,0xbe6c9a7f,0xbf791298,0xbeb554ec,0xbf6f6830,
0x3f226799,0xbf45e403,0x3f0b9a6b,0xbf5695e5,0x3ee63375,0xbf64aa59,0x3eb263ef,0xbf6ff573,0x3e78cfcc,0xbf7853f8,0x3e09cf86,0xbf7dabcc,0x3cc90ab0,0xbf7fec43,0xbdafb680,0xbf7f0e58,
0x3ef15aea,0xbf61c598,0x3eb263ef,0xbf6ff573,0x3e605c13,0xbf79c79d,0x3dafb680,0xbf7f0e58,0xbd48fb30,0xbf7fb10f,0xbe3b6ecf,0xbf7baccd,0xbea09ae5,0xbf731447,0xbee0924f,0xbf660f88,
0x3f187fc0,0xbf4d9f02,0x3eff17b2,0xbf5df6be,0x3ec9b953,0xbf6b4b0c,0x3e919ddd,0xbf756d97,0x3e2f10a2,0xbf7c3b28,0x3d621469,0xbf7f9c18,0xbd7b2b74,0xbf7f84ab,0xbe354098,0xbf7bf531,
0x3edae880,0xbf676bd8,0x3e97a117,0xbf748422,0x3e22abb6,0xbf7cbfc9,0x3c96c9b6,0xbf7ff4e6,0xbdfab273,0xbf7e1324,0xbe8586ce,0xbf772417,0xbec9b953,0xbf6b4b0c,0xbf04f484,0xbf5ac450,
0x3ec3ef15,0xbf6c835e,0x3e78cfcc,0xbf7853f8,0x3dc8bd36,0xbf7ec46d,0xbd48fb30,0xbf7fb10f,0xbe47c5c2,0xbf7b14be,0xbeac7cd4,0xbf710908,0xbef15aea,0xbf61c598,0xbf187fc0,0xbf4d9f02,
0x3e47c5c2,0xbf7b14be,0x3cc90ab0,0xbf7fec43,0xbe164083,0xbf7d3aac,0xbea09ae5,0xbf731447,0xbef15aea,0xbf61c598,0xbf1d7fd1,0xbf49d112,0xbf3daef9,0xbf2beb4a,0xbf584853,0xbf08f59b,
0x3eac7cd4,0xbf710908,0x3e419b37,0xbf7b61fc,0x3d16c32c,0xbf7fd397,0xbdee3876,0xbf7e4323,0xbe888e93,0xbf76ba07,0xbed25a09,0xbf696591,0xbf0b9a6b,0xbf5695e5,0xbf2ac082,0xbf3ebc1b,
0x3e164083,0xbf7d3aac,0xbcfb49ba,0xbf7fe129,0xbe541501,0xbf7a7302,0xbec1071e,0xbf6d1c1d,0xbf08f59b,0xbf584853,0xbf2d1469,0xbf3ca003,0xbf4bbbf8,0xbf1b02c6,0xbf63f473,0xbee900b7,
0x3e94a031,0xbf74fa0b,0x3e09cf86,0xbf7dabcc,0xbcc90ab0,0xbf7fec43,0xbe3b6ecf,0xbf7baccd,0xbeac7cd4,0xbf710908,0xbef6e0cb,0xbf604621,0xbf1d7fd1,0xbf49d112,0xbf3b8f3b,0xbf2e3bde,
0x3dc8bd36,0xbf7ec46d,0xbdafb680,0xbf7f0e58,0xbe888e93,0xbf76ba07,0xbee0924f,0xbf660f88,0xbf187fc0,0xbf4d9f02,0xbf3b8f3b,0xbf2e3bde,0xbf584853,0xbf08f59b,0xbf6db293,0xbebe1d4a,
0x3e78cfcc,0xbf7853f8,0x3da3308c,0xbf7f2f9d,0xbdafb680,0xbf7f0e58,0xbe7ee6e1,0xbf77f110,0xbecf7bca,0xbf6a09a7,0xbf0cead0,0xbf55b993,0xbf2e3bde,0xbf3b8f3b,0xbf4ac77f,0xbf1c420c,
0x3d48fb30,0xbf7fb10f,0xbe1008b7,0xbf7d7474,0xbea68f12,0xbf721352,0xbeff17b2,0xbf5df6be,0xbf273656,0xbf41d870,0xbf48d8b3,0xbf1ebc12,0xbf633c5a,0xbeebcbbb,0xbf756d97,0xbe919ddd,
0x3f800000,0x0,0x3f800000,0x0,0x3f800000,0x0,0x3f800000,0x0,0x3f800000,0x0,0x3f800000,0x0,0x3f800000,0x0,0x3f800000,0x0,
0x3f6c835e,0xbec3ef15,0x3f6a09a7,0xbecf7bca,0x3f676bd8,0xbedae880,0x3f64aa59,0xbee63375,0x3f61c598,0xbef15aea,0x3f5ebe05,0xbefc5d27,0x3f5b941a,0xbf039c3d,0x3f584853,0xbf08f59b,
0x3f7ec46d,0xbdc8bd36,0x3f7e9bc9,0xbdd53db9,0x3f7e70b0,0xbde1bc2e,0x3f7e4323,0xbdee3876,0x3f7e1324,0xbdfab273,0x3f7de0b1,0xbe039502,0x3f7dabcc,0xbe09cf86,0x3f7d7474,0xbe1008b7,
0x3f61c598,0xbef15aea,0x3f5df6be,0xbeff17b2,0x3f59f26a,0xbf064b82,0x3f55b993,0xbf0cead0,0x3f514d3d,0xbf13682a,0x3f4cae79,0xbf19c200,0x3f47de65,0xbf1ff6cb,0x3f42de29,0xbf26050a,
0x3f7b14be,0xbe47c5c2,0x3f7a7302,0xbe541501,0x3f79c79d,0xbe605c13,0x3f791298,0xbe6c9a7f,0x3f7853f8,0xbe78cfcc,0x3f778bc5,0xbe827dc0,0x3f76ba07,0xbe888e93,0x3f75dec6,0xbe8e9a22,
0x3f54db31,0xbf0e39da,0x3f4f7a1f,0xbf15f6d9,0x3f49d112,0xbf1d7fd1,0x3f43e200,0xbf24d225,0x3f3daef9,0xbf2beb4a,0x3f373a23,0xbf32c8c9,0x3f3085bb,0xbf396842,0x3f299415,0xbf3fc767,
0x3f74fa0b,0xbe94a031,0x3f73913f,0xbe9d9e78,0x3f721352,0xbea68f12,0x3f708066,0xbeaf713a,0x3f6ed89e,0xbeb8442a,0x3f6d1c1d,0xbec1071e,0x3f6b4b0c,0xbec9b953,0x3f696591,0xbed25a09,
0x3f45e403,0xbf226799,0x3f3ebc1b,0xbf2ac082,0x3f373a23,0xbf32c8c9,0x3f2f61a5,0xbf3a7ca4,0x3f273656,0xbf41d870,0x3f1ebc12,0xbf48d8b3,0x3f15f6d9,0xbf4f7a1f,0x3f0cead0,0xbf55b993,
0x3f3504f3,0xbf3504f3,0x3f2beb4a,0xbf3daef9,0x3f226799,0xbf45e403,0x3f187fc0,0xbf4d9f02,0x3f0e39da,0xbf54db31,0x3f039c3d,0xbf5b941a,0x3ef15aea,0xbf61c598,0x3edae880,0xbf676bd8,
0x3ec3ef15,0xbf6c835e,0x3ea09ae5,0xbf731447,0x3e78cfcc,0xbf7853f8,0x3e2f10a2,0xbf7c3b28,0x3dc8bd36,0xbf7ec46d,0x3cc90ab0,0xbf7fec43,0xbd48fb30,0xbf7fb10f,0xbdfab273,0xbf7e1324,
0x3f226799,0xbf45e403,0x3f173c07,0xbf4e8d90,0x3f0b9a6b,0xbf5695e5,0x3eff17b2,0xbf5df6be,0x3ee63375,0xbf64aa59,0x3ecc9b8b,0xbf6aab7b,0x3eb263ef,0xbf6ff573,0x3e97a117,0xbf748422,
0x3e94a031,0xbf74fa0b,0x3e5a3997,0xbf7a1e84,0x3e09cf86,0xbf7dabcc,0x3d621469,0xbf7f9c18,0xbcc90ab0,0xbf7fec43,0xbdd53db9,0xbf7e9bc9,0xbe3b6ecf,0xbf7baccd,0xbe8586ce,0xbf772417,
0x3f0e39da,0xbf54db31,0x3f00e7e4,0xbf5d2d53,0x3ee63375,0xbf64aa59,0x3ec9b953,0xbf6b4b0c,0x3eac7cd4,0xbf710908,0x3e8e9a22,0xbf75dec6,0x3e605c13,0xbf79c79d,0x3e22abb6,0xbf7cbfc9,
0x3e47c5c2,0xbf7b14be,0x3de1bc2e,0xbf7e70b0,0x3cc90ab0,0xbf7fec43,0xbd7b2b74,0xbf7f84ab,0xbe164083,0xbf7d3aac,0xbe6c9a7f,0xbf791298,0xbea09ae5,0xbf731447,0xbec9b953,0xbf6b4b0c,
0x3ef15aea,0xbf61c598,0x3ed25a09,0xbf696591,0x3eb263ef,0xbf6ff573,0x3e919ddd,0xbf756d97,0x3e605c13,0xbf79c79d,0x3e1c76de,0xbf7cfe73,0x3dafb680,0xbf7f0e58,0x3c96c9b6,0xbf7ff4e6,
0x3dc8bd36,0xbf7ec46d,0x3bc90f88,0xbf7ffec4,0xbdafb680,0xbf7f0e58,0xbe354098,0xbf7bf531,0xbe888e93,0xbf76ba07,0xbeb554ec,0xbf6f6830,0xbee0924f,0xbf660f88,0xbf04f484,0xbf5ac450,
0x0,0xbf800000,0xbdc8bd36,0xbf7ec46d,0xbe47c5c2,0xbf7b14be,0xbe94a031,0xbf74fa0b,0xbec3ef15,0xbf6c835e,0xbef15aea,0xbf61c598,0xbf0e39da,0xbf54db31,0xbf226799,0xbf45e403,
0xbec3ef15,0xbf6c835e,0xbefc5d27,0xbf5ebe05,0xbf187fc0,0xbf4d9f02,0xbf3085bb,0xbf396842,0xbf45e403,0xbf226799,0xbf584853,0xbf08f59b,0xbf676bd8,0xbedae880,0xbf731447,0xbea09ae5,
0xbdc8bd36,0xbf7ec46d,0xbe4dee60,0xbf7ac516,0xbe9aa086,0xbf740bdd,0xbecc9b8b,0xbf6aab7b,0xbefc5d27,0xbf5ebe05,0xbf14b039,0xbf5064af,0xbf299415,0xbf3fc767,0xbf3ca003,0xbf2d1469,
0xbef15aea,0xbf61c598,0xbf14b039,0xbf5064af,0xbf2e3bde,0xbf3b8f3b,0xbf44e3f5,0xbf239da9,0xbf584853,0xbf08f59b,0xbf6816a8,0xbed8106b,0xbf740bdd,0xbe9aa086,0xbf7bf531,0xbe354098,
0xbe47c5c2,0xbf7b14be,0xbe9aa086,0xbf740bdd,0xbecf7bca,0xbf6a09a7,0xbf00e7e4,0xbf5d2d53,0xbf187fc0,0xbf4d9f02,0xbf2e3bde,0xbf3b8f3b,0xbf41d870,0xbf273656,0xbf531849,0xbf10d3cd,
0xbf0e39da,0xbf54db31,0xbf299415,0xbf3fc767,0xbf41d870,0xbf273656,0xbf5695e5,0xbf0b9a6b,0xbf676bd8,0xbedae880,0xbf740bdd,0xbe9aa086,0xbf7c3b28,0xbe2f10a2,0xbf7fd397,0xbd16c32c,
0xbe94a031,0xbf74fa0b,0xbecc9b8b,0xbf6aab7b,0xbf00e7e4,0xbf5d2d53,0xbf19c200,0xbf4cae79,0xbf3085bb,0xbf396842,0xbf44e3f5,0xbf239da9,0xbf5695e5,0xbf0b9a6b,0xbf655e0b,0xbee363fa,
0xbf226799,0xbf45e403,0xbf3ca003,0xbf2d1469,0xbf531849,0xbf10d3cd,0xbf655e0b,0xbee363fa,0xbf731447,0xbea09ae5,0xbf7bf531,0xbe354098,0xbf7fd397,0xbd16c32c,0xbf7e9bc9,0x3dd53db9,
0xbf3504f3,0xbf3504f3,0xbf4d9f02,0xbf187fc0,0xbf61c598,0xbef15aea,0xbf710908,0xbeac7cd4,0xbf7b14be,0xbe47c5c2,0xbf7fb10f,0xbd48fb30,0xbf7ec46d,0x3dc8bd36,0xbf7853f8,0x3e78cfcc,
0xbf6c835e,0xbec3ef15,0xbf79c79d,0xbe605c13,0xbf7fb10f,0xbd48fb30,0xbf7e1324,0x3dfab273,0xbf74fa0b,0x3e94a031,0xbf64aa59,0x3ee63375,0xbf4d9f02,0x3f187fc0,0xbf3085bb,0x3f396842,
0xbf45e403,0xbf226799,0xbf5c61c7,0xbf0242b1,0xbf6db293,0xbebe1d4a,0xbf796e4e,0xbe667c66,0xbf7f4e6d,0xbd96a905,0xbf7f2f9d,0x3da3308c,0xbf791298,0x3e6c9a7f,0xbf6d1c1d,0x3ec1071e,
0xbf74fa0b,0xbe94a031,0xbf7e4323,0xbdee3876,0xbf7f84ab,0x3d7b2b74,0xbf78b47b,0x3e72b651,0xbf6a09a7,0x3ecf7bca,0xbf53fac3,0x3f0f8784,0xbf373a23,0x3f32c8c9,0xbf14b039,0x3f5064af,
0xbf54db31,0xbf0e39da,0xbf68bf3c,0xbed53641,0xbf76ba07,0xbe888e93,0xbf7e70b0,0xbde1bc2e,0xbf7fb10f,0x3d48fb30,0xbf7a7302,0x3e541501,0xbf6ed89e,0x3eb8442a,0xbf5d2d53,0x3f00e7e4,
0xbf7b14be,0xbe47c5c2,0xbf7ffb11,0xbc490e90,0xbf7c3b28,0x3e2f10a2,0xbf6ff573,0x3eb263ef,0xbf5b941a,0x3f039c3d,0xbf3fc767,0x3f299415,0xbf1d7fd1,0x3f49d112,0xbeebcbbb,0x3f633c5a,
0xbf61c598,0xbef15aea,0xbf7294f8,0xbea395c5,0xbf7cbfc9,0xbe22abb6,0xbf7ffec4,0x3bc90f88,0xbf7c3b28,0x3e2f10a2,0xbf718f57,0x3ea986c4,0xbf604621,0x3ef6e0cb,0xbf48d8b3,0x3f1ebc12,
0xbf7ec46d,0xbdc8bd36,0xbf7eea9d,0x3dbc3ac3,0xbf75dec6,0x3e8e9a22,0xbf63f473,0x3ee900b7,0xbf49d112,0x3f1d7fd1,0xbf286605,0x3f40d0da,0xbf00e7e4,0x3f5d2d53,0xbea986c4,0x3f718f57,
0x3f800000,0x0,0x3f800000,0x0,0x3f800000,0x0,0x3f800000,0x0,0x3f800000,0x0,0x3f800000,0x0,0x3f800000,0x0,0x3f800000,0x0,
0x3f54db31,0xbf0e39da,0x3f514d3d,0xbf13682a,0x3f4d9f02,0xbf187fc0,0x3f49d112,0xbf1d7fd1,0x3f45e403,0xbf226799,0x3f41d870,0xbf273656,0x3f3daef9,0xbf2beb4a,0x3f396842,0xbf3085bb,
0x3f7d3aac,0xbe164083,0x3f7cfe73,0xbe1c76de,0x3f7cbfc9,0xbe22abb6,0x3f7c7eb0,0xbe28defc,0x3f7c3b28,0xbe2f10a2,0x3f7bf531,0xbe354098,0x3f7baccd,0xbe3b6ecf,0x3f7b61fc,0xbe419b37,
0x3f3daef9,0xbf2beb4a,0x3f385216,0xbf31a81d,0x3f32c8c9,0xbf373a23,0x3f2d1469,0xbf3ca003,0x3f273656,0xbf41d870,0x3f212ff9,0xbf46e22a,0x3f1b02c6,0xbf4bbbf8,0x3f14b039,0xbf5064af,
0x3f74fa0b,0xbe94a031,0x3f740bdd,0xbe9aa086,0x3f731447,0xbea09ae5,0x3f721352,0xbea68f12,0x3f710908,0xbeac7cd4,0x3f6ff573,0xbeb263ef,0x3f6ed89e,0xbeb8442a,0x3f6db293,0xbebe1d4a,
0x3f226799,0xbf45e403,0x3f1b02c6,0xbf4bbbf8,0x3f13682a,0xbf514d3d,0x3f0b9a6b,0xbf5695e5,0x3f039c3d,0xbf5b941a,0x3ef6e0cb,0xbf604621,0x3ee63375,0xbf64aa59,0x3ed53641,0xbf68bf3c,
0x3f676bd8,0xbedae880,0x3f655e0b,0xbee363fa,0x3f633c5a,0xbeebcbbb,0x3f6106f2,0xbef41f07,0x3f5ebe05,0xbefc5d27,0x3f5c61c7,0xbf0242b1,0x3f59f26a,0xbf064b82,0x3f577026,0xbf0a48ad,
0x3f039c3d,0xbf5b941a,0x3ef41f07,0xbf6106f2,0x3ee0924f,0xbf660f88,0x3ecc9b8b,0xbf6aab7b,0x3eb8442a,0xbf6ed89e,0x3ea395c5,0xbf7294f8,0x3e8e9a22,0xbf75dec6,0x3e72b651,0xbf78b47b,
0x3ec3ef15,0xbf6c835e,0x3eac7cd4,0xbf710908,0x3e94a031,0xbf74fa0b,0x3e78cfcc,0xbf7853f8,0x3e47c5c2,0xbf7b14be,0x3e164083,0xbf7d3aac,0x3dc8bd36,0xbf7ec46d,0x3d48fb30,0xbf7fb10f,
0xbe47c5c2,0xbf7b14be,0xbe888e93,0xbf76ba07,0xbeac7cd4,0xbf710908,0xbecf7bca,0xbf6a09a7,0xbef15aea,0xbf61c598,0xbf08f59b,0xbf584853,0xbf187fc0,0xbf4d9f02,0xbf273656,0xbf41d870,
0x3e78cfcc,0xbf7853f8,0x3e419b37,0xbf7b61fc,0x3e09cf86,0xbf7dabcc,0x3da3308c,0xbf7f2f9d,0x3cc90ab0,0xbf7fec43,0xbcfb49ba,0xbf7fe129,0xbdafb680,0xbf7f0e58,0xbe1008b7,0xbf7d7474,
0xbeac7cd4,0xbf710908,0xbed25a09,0xbf696591,0xbef6e0cb,0xbf604621,0xbf0cead0,0xbf55b993,0xbf1d7fd1,0xbf49d112,0xbf2d1469,0xbf3ca003,0xbf3b8f3b,0xbf2e3bde,0xbf48d8b3,0xbf1ebc12,
0x3dc8bd36,0xbf7ec46d,0x3d16c32c,0xbf7fd397,0xbcc90ab0,0xbf7fec43,0xbdafb680,0xbf7f0e58,0xbe164083,0xbf7d3aac,0xbe541501,0xbf7a7302,0xbe888e93,0xbf76ba07,0xbea68f12,0xbf721352,
0xbef15aea,0xbf61c598,0xbf0b9a6b,0xbf5695e5,0xbf1d7fd1,0xbf49d112,0xbf2e3bde,0xbf3b8f3b,0xbf3daef9,0xbf2beb4a,0xbf4bbbf8,0xbf1b02c6,0xbf584853,0xbf08f59b,0xbf633c5a,0xbeebcbbb,
0xbd48fb30,0xbf7fb10f,0xbdee3876,0xbf7e4323,0xbe3b6ecf,0xbf7baccd,0xbe7ee6e1,0xbf77f110,0xbea09ae5,0xbf731447,0xbec1071e,0xbf6d1c1d,0xbee0924f,0xbf660f88,0xbeff17b2,0xbf5df6be,
0xbf187fc0,0xbf4d9f02,0xbf2ac082,0xbf3ebc1b,0xbf3b8f3b,0xbf2e3bde,0xbf4ac77f,0xbf1c420c,0xbf584853,0xbf08f59b,0xbf63f473,0xbee900b7,0xbf6db293,0xbebe1d4a,0xbf756d97,0xbe919ddd,
0xbf3504f3,0xbf3504f3,0xbf45e403,0xbf226799,0xbf54db31,0xbf0e39da,0xbf61c598,0xbef15aea,0xbf6c835e,0xbec3ef15,0xbf74fa0b,0xbe94a031,0xbf7b14be,0xbe47c5c2,0xbf7ec46d,0xbdc8bd36,
0xbf7b14be,0xbe47c5c2,0xbf7f4e6d,0xbd96a905,0xbf7fb10f,0x3d48fb30,0xbf7c3b28,0x3e2f10a2,0xbf74fa0b,0x3e94a031,0xbf6a09a7,0x3ecf7bca,0xbf5b941a,0x3f039c3d,0xbf49d112,0x3f1d7fd1,
0xbf4d9f02,0xbf187fc0,0xbf5c61c7,0xbf0242b1,0xbf68bf3c,0xbed53641,0xbf7294f8,0xbea395c5,0xbf79c79d,0xbe605c13,0xbf7e4323,0xbdee3876,0xbf7ffb11,0xbc490e90,0xbf7eea9d,0x3dbc3ac3,
0xbf7fb10f,0xbd48fb30,0xbf7f2f9d,0x3da3308c,0xbf7a7302,0x3e541501,0xbf718f57,0x3ea986c4,0xbf64aa59,0x3ee63375,0xbf53fac3,0x3f0f8784,0xbf3fc767,0x3f299415,0xbf286605,0x3f40d0da,
0xbf61c598,0xbef15aea,0xbf6db293,0xbebe1d4a,0xbf76ba07,0xbe888e93,0xbf7cbfc9,0xbe22abb6,0xbf7fb10f,0xbd48fb30,0xbf7f84ab,0x3d7b2b74,0xbf7c3b28,0x3e2f10a2,0xbf75dec6,0x3e8e9a22,
0xbf7ec46d,0x3dc8bd36,0xbf791298,0x3e6c9a7f,0xbf6ed89e,0x3eb8442a,0xbf604621,0x3ef6e0cb,0xbf4d9f02,0x3f187fc0,0xbf373a23,0x3f32c8c9,0xbf1d7fd1,0x3f49d112,0xbf00e7e4,0x3f5d2d53,
0xbf710908,0xbeac7cd4,0xbf796e4e,0xbe667c66,0xbf7e70b0,0xbde1bc2e,0xbf7ffec4,0x3bc90f88,0xbf7e1324,0x3dfab273,0xbf78b47b,0x3e72b651,0xbf6ff573,0x3eb263ef,0xbf63f473,0x3ee900b7,
0xbf7853f8,0x3e78cfcc,0xbf6d1c1d,0x3ec1071e,0xbf5d2d53,0x3f00e7e4,0xbf48d8b3,0x3f1ebc12,0xbf3085bb,0x3f396842,0xbf14b039,0x3f5064af,0xbeebcbbb,0x3f633c5a,0xbea986c4,0x3f718f57,
0xbf6c835e,0x3ec3ef15,0xbf5b941a,0x3f039c3d,0xbf45e403,0x3f226799,0xbf2beb4a,0x3f3daef9,0xbf0e39da,0x3f54db31,0xbedae880,0x3f676bd8,0xbe94a031,0x3f74fa0b,0xbe164083,0x3f7d3aac,
0xbf0e39da,0x3f54db31,0xbecf7bca,0x3f6a09a7,0xbe78cfcc,0x3f7853f8,0xbd96a905,0x3f7f4e6d,0x3dc8bd36,0x3f7ec46d,0x3e888e93,0x3f76ba07,0x3edae880,0x3f676bd8,0x3f13682a,0x3f514d3d,
0xbf5b941a,0x3f039c3d,0xbf44e3f5,0x3f239da9,0xbf299415,0x3f3fc767,0xbf0a48ad,0x3f577026,0xbecf7bca,0x3f6a09a7,0xbe8586ce,0x3f772417,0xbde1bc2e,0x3f7e70b0,0x3d2fe007,0x3f7fc38f,
0xbedae880,0x3f676bd8,0xbe8586ce,0x3f772417,0xbdafb680,0x3f7f0e58,0x3dbc3ac3,0x3f7eea9d,0x3e888e93,0x3f76ba07,0x3eddbe79,0x3f66becc,0x3f15f6d9,0x3f4f7a1f,0x3f385216,0x3f31a81d,
0xbf45e403,0x3f226799,0xbf299415,0x3f3fc767,0xbf08f59b,0x3f584853,0xbec9b953,0x3f6b4b0c,0xbe78cfcc,0x3f7853f8,0xbdafb680,0x3f7f0e58,0x3d96a905,0x3f7f4e6d,0x3e6c9a7f,0x3f791298,
0xbe94a031,0x3f74fa0b,0xbde1bc2e,0x3f7e70b0,0x3d96a905,0x3f7f4e6d,0x3e827dc0,0x3f778bc5,0x3edae880,0x3f676bd8,0x3f15f6d9,0x3f4f7a1f,0x3f396842,0x3f3085bb,0x3f5695e5,0x3f0b9a6b,
0xbf2beb4a,0x3f3daef9,0xbf0a48ad,0x3f577026,0xbec9b953,0x3f6b4b0c,0xbe72b651,0x3f78b47b,0xbd96a905,0x3f7f4e6d,0x3dbc3ac3,0x3f7eea9d,0x3e827dc0,0x3f778bc5,0x3ed25a09,0x3f696591,
0xbe164083,0x3f7d3aac,0x3d2fe007,0x3f7fc38f,0x3e6c9a7f,0x3f791298,0x3ed25a09,0x3f696591,0x3f13682a,0x3f514d3d,0x3f385216,0x3f31a81d,0x3f5695e5,0x3f0b9a6b,0x3f6d1c1d,0x3ec1071e,
0x3e00,0x3e00,0x3e00,0x3e00,0x3e00,0x3e00,0x3e00,0x3e00,0x3e00,0x3e00,0x3e00,0x3e00,0x3e00,0x3e00,0x3e00,0x3e00,
0xbd443ded,0xbcc83dfb,0xbc493dff,0xbd153df5,0xbdb53db5,0xbdd53d8e,0xbdc63da2,0xbde23d71,0xbe000000,0xbdfbbcc8,0xbdffbc49,0xbdf5bd15,0xbdb5bdb5,0xbd8ebdd5,0xbda2bdc6,0xbd71bde2,
0xbdb53db5,0xbd443ded,0xbcc83dfb,0xbd8e3dd5,0xbe000000,0xbdedbd44,0xbdfbbcc8,0xbdd5bd8e,0xbe00,0x3d44bded,0x3cc8bdfb,0x3d8ebdd5,0x3e000000,0x3ded3d44,0x3dfb3cc8,0x3dd53d8e,
0xbded3d44,0xbd8e3dd5,0xbd153df5,0xbdc63da2,0xbdb5bdb5,0xbcc8bdfb,0xbd71bde2,0x3c49bdff,0x3e000000,0x3dd53d8e,0x3df53d15,0x3da23dc6,0xbdb53db5,0xbdfb3cc8,0xbde23d71,0xbdffbc49,
0xbe000000,0xbdb53db5,0xbd443ded,0xbded3d44,0xbe00,0x3db5bdb5,0x3d44bded,0x3dedbd44,0x3e00,0xbdb53db5,0xbd443ded,0xbded3d44,0xbe00,0x3db5bdb5,0x3d44bded,0x3dedbd44,
0xbdedbd44,0xbdd53d8e,0xbd713de2,0xbdff3c49,0x3db5bdb5,0x3dfb3cc8,0x3df5bd15,0x3dc63da2,0xbe000000,0xbd8ebdd5,0xbde2bd71,0xbc49bdff,0x3db53db5,0xbcc83dfb,0x3d153df5,0xbda23dc6,
0xbdb5bdb5,0xbded3d44,0xbd8e3dd5,0xbdfbbcc8,0x3e000000,0x3d443ded,0x3dd53d8e,0xbcc83dfb,0xbe00,0x3dedbd44,0x3d8ebdd5,0x3dfb3cc8,0xbe000000,0xbd44bded,0xbdd5bd8e,0x3cc8bdfb,
0xbd44bded,0xbdfb3cc8,0xbda23dc6,0xbde2bd71,0x3db53db5,0xbd8e3dd5,0x3c493dff,0xbdf53d15,0x3e000000,0x3cc83dfb,0x3dc63da2,0xbd713de2,0x3db5bdb5,0x3dd53d8e,0x3dffbc49,0x3d153df5,
0xbe00,0xbe000000,0xbdb53db5,0xbdb5bdb5,0x3e00,0xbe000000,0xbdb53db5,0xbdb5bdb5,0x3e00,0xbe000000,0xbdb53db5,0xbdb5bdb5,0x3e00,0xbe000000,0xbdb53db5,0xbdb5bdb5,
0x3d44bded,0xbdfbbcc8,0xbdc63da2,0xbd71bde2,0xbdb53db5,0xbd8ebdd5,0xbdffbc49,0x3d15bdf5,0xbe000000,0x3cc8bdfb,0xbda2bdc6,0x3de2bd71,0xbdb5bdb5,0x3dd5bd8e,0x3c49bdff,0x3df53d15,
0x3db5bdb5,0xbdedbd44,0xbdd53d8e,0xbcc8bdfb,0xbe000000,0x3d44bded,0xbd8ebdd5,0x3dfbbcc8,0xbe00,0x3ded3d44,0x3dd5bd8e,0x3cc83dfb,0x3e000000,0xbd443ded,0x3d8e3dd5,0xbdfb3cc8,
0x3dedbd44,0xbdd5bd8e,0xbde23d71,0x3c49bdff,0xbdb5bdb5,0x3dfbbcc8,0x3d15bdf5,0x3da23dc6,0x3e000000,0xbd8e3dd5,0x3d713de2,0xbdffbc49,0xbdb53db5,0xbcc8bdfb,0xbdf5bd15,0x3dc6bda2,
0x3e000000,0xbdb5bdb5,0xbded3d44,0x3d44bded,0xbe00,0x3db53db5,0x3dedbd44,0xbd443ded,0x3e00,0xbdb5bdb5,0xbded3d44,0x3d44bded,0xbe00,0x3db53db5,0x3dedbd44,0xbd443ded,
0x3ded3d44,0xbd8ebdd5,0xbdf53d15,0x3da2bdc6,0x3db5bdb5,0xbcc83dfb,0x3de23d71,0xbdff3c49,0xbe000000,0x3dd5bd8e,0xbd15bdf5,0x3dc63da2,0x3db53db5,0xbdfbbcc8,0xbd713de2,0xbc49bdff,
0x3db53db5,0xbd44bded,0xbdfb3cc8,0x3dd5bd8e,0x3e000000,0xbded3d44,0x3cc83dfb,0xbd8ebdd5,0xbe00,0x3d443ded,0x3dfbbcc8,0xbdd53d8e,0xbe000000,0x3dedbd44,0xbcc8bdfb,0x3d8e3dd5,
0x3d443ded,0xbcc8bdfb,0xbdff3c49,0x3df5bd15,0x3db53db5,0xbdd5bd8e,0xbda23dc6,0x3d71bde2,0x3e000000,0xbdfb3cc8,0x3c493dff,0xbd15bdf5,0x3db5bdb5,0xbd8e3dd5,0x3dc63da2,0xbde2bd71,
0x3e00,0xbe00,0xbe000000,0x3e000000,0x3e00,0xbe00,0xbe000000,0x3e000000,0x3e00,0xbe00,0xbe000000,0x3e000000,0x3e00,0xbe00,0xbe000000,0x3e000000,
0xbd443ded,0x3cc8bdfb,0xbdffbc49,0x3df53d15,0xbdb53db5,0x3dd5bd8e,0xbda2bdc6,0x3d713de2,0xbe000000,0x3dfb3cc8,0x3c49bdff,0xbd153df5,0xbdb5bdb5,0x3d8e3dd5,0x3dc6bda2,0xbde23d71,
0xbdb53db5,0x3d44bded,0xbdfbbcc8,0x3dd53d8e,0xbe000000,0x3ded3d44,0x3cc8bdfb,0xbd8e3dd5,0xbe00,0xbd443ded,0x3dfb3cc8,0xbdd5bd8e,0x3e000000,0xbdedbd44,0xbcc83dfb,0x3d8ebdd5,
0xbded3d44,0x3d8ebdd5,0xbdf5bd15,0x3da23dc6,0xbdb5bdb5,0x3cc83dfb,0x3de2bd71,0xbdffbc49,0x3e000000,0xbdd5bd8e,0xbd153df5,0x3dc6bda2,0xbdb53db5,0x3dfbbcc8,0xbd71bde2,0xbc493dff,
0xbe000000,0x3db5bdb5,0xbdedbd44,0x3d443ded,0xbe00,0xbdb53db5,0x3ded3d44,0xbd44bded,0x3e00,0x3db5bdb5,0xbdedbd44,0x3d443ded,0xbe00,0xbdb53db5,0x3ded3d44,0xbd44bded,
0xbdedbd44,0x3dd5bd8e,0xbde2bd71,0x3c493dff,0x3db5bdb5,0xbdfbbcc8,0x3d153df5,0x3da2bdc6,0xbe000000,0x3d8e3dd5,0x3d71bde2,0xbdff3c49,0x3db53db5,0x3cc8bdfb,0xbdf53d15,0x3dc63da2,
0xbdb5bdb5,0x3dedbd44,0xbdd5bd8e,0xbcc83dfb,0x3e000000,0xbd44bded,0xbd8e3dd5,0x3dfb3cc8,0xbe00,0xbded3d44,0x3dd53d8e,0x3cc8bdfb,0xbe000000,0x3d443ded,0x3d8ebdd5,0xbdfbbcc8,
0xbd44bded,0x3dfbbcc8,0xbdc6bda2,0xbd713de2,0x3db53db5,0x3d8ebdd5,0xbdff3c49,0x3d153df5,0x3e000000,0xbcc8bdfb,0xbda23dc6,0x3de23d71,0x3db5bdb5,0xbdd5bd8e,0x3c493dff,0x3df5bd15,
0xbe00,0x3e000000,0xbdb5bdb5,0xbdb53db5,0x3e00,0x3e000000,0xbdb5bdb5,0xbdb53db5,0x3e00,0x3e000000,0xbdb5bdb5,0xbdb53db5,0x3e00,0x3e000000,0xbdb5bdb5,0xbdb53db5,
0x3d44bded,0x3dfb3cc8,0xbda2bdc6,0xbde23d71,0xbdb53db5,0x3d8e3dd5,0x3c49bdff,0xbdf5bd15,0xbe000000,0xbcc83dfb,0x3dc6bda2,0xbd71bde2,0xbdb5bdb5,0xbdd53d8e,0x3dff3c49,0x3d15bdf5,
0x3db5bdb5,0x3ded3d44,0xbd8ebdd5,0xbdfb3cc8,0xbe000000,0xbd443ded,0x3dd5bd8e,0xbcc8bdfb,0xbe00,0xbdedbd44,0x3d8e3dd5,0x3dfbbcc8,0x3e000000,0x3d44bded,0xbdd53d8e,0x3cc83dfb,
0x3dedbd44,0x3dd53d8e,0xbd71bde2,0xbdffbc49,0xbdb5bdb5,0xbdfb3cc8,0x3df53d15,0x3dc6bda2,0x3e000000,0x3d8ebdd5,0xbde23d71,0xbc493dff,0xbdb53db5,0x3cc83dfb,0x3d15bdf5,0xbda2bdc6,
0x3e000000,0x3db53db5,0xbd44bded,0xbdedbd44,0xbe00,0xbdb5bdb5,0x3d443ded,0x3ded3d44,0x3e00,0x3db53db5,0xbd44bded,0xbdedbd44,0xbe00,0xbdb5bdb5,0x3d443ded,0x3ded3d44,
0x3ded3d44,0x3d8e3dd5,0xbd15bdf5,0xbdc6bda2,0x3db5bdb5,0x3cc8bdfb,0xbd713de2,0x3c493dff,0xbe000000,0xbdd53d8e,0x3df5bd15,0x3da2bdc6,0x3db53db5,0x3dfb3cc8,0xbde2bd71,0xbdff3c49,
0x3db53db5,0x3d443ded,0xbcc8bdfb,0xbd8ebdd5,0x3e000000,0x3dedbd44,0xbdfb3cc8,0xbdd53d8e,0xbe00,0xbd44bded,0x3cc83dfb,0x3d8e3dd5,0xbe000000,0xbded3d44,0x3dfbbcc8,0x3dd5bd8e,
0x3d443ded,0x3cc83dfb,0xbc49bdff,0xbd15bdf5,0x3db53db5,0x3dd53d8e,0xbdc6bda2,0xbde2bd71,0x3e000000,0x3dfbbcc8,0xbdff3c49,0xbdf53d15,0x3db5bdb5,0x3d8ebdd5,0xbda23dc6,0xbd713de2,
0x3d803d80,0x3e00,0x3e00,0x3e00,0x3e00,0x3e00,0x3e00,0x3e00,0x3e00,0x3e00,0x3e00,0x3e00,0x3e00,0x3e00,0x3e00,0x3e00,
0xbd803d80,0x3cc8bdfb,0x3c49bdff,0x3d15bdf5,0xbded3d44,0x3dd5bd8e,0x3dc6bda2,0x3de2bd71,0xbdedbd44,0x3dfb3cc8,0x3dff3c49,0x3df53d15,0xbd44bded,0x3d8e3dd5,0x3da23dc6,0x3d713de2,
0x3d803d80,0xbd443ded,0xbcc83dfb,0xbd8e3dd5,0xbdb5bdb5,0xbdedbd44,0xbdfbbcc8,0xbdd5bd8e,0x3db5bdb5,0x3d44bded,0x3cc8bdfb,0x3d8ebdd5,0x3db53db5,0x3ded3d44,0x3dfb3cc8,0x3dd53d8e,
0xbd803d80,0x3d8ebdd5,0x3d15bdf5,0x3dc6bda2,0x3d44bded,0x3cc83dfb,0x3d713de2,0xbc493dff,0x3d443ded,0xbdd5bd8e,0xbdf5bd15,0xbda2bdc6,0xbdedbd44,0x3dfbbcc8,0x3de2bd71,0x3dff3c49,
0x3d803d80,0xbdb53db5,0xbd443ded,0xbded3d44,0x3e000000,0x3db5bdb5,0x3d44bded,0x3dedbd44,0xbe000000,0xbdb53db5,0xbd443ded,0xbded3d44,0x3e000000,0x3db5bdb5,0x3d44bded,0x3dedbd44,
0xbd803d80,0x3dd5bd8e,0x3d71bde2,0x3dffbc49,0x3d443ded,0xbdfbbcc8,0xbdf53d15,0xbdc6bda2,0x3d44bded,0x3d8e3dd5,0x3de23d71,0x3c493dff,0xbded3d44,0x3cc8bdfb,0xbd15bdf5,0x3da2bdc6,
0x3d803d80,0xbded3d44,0xbd8e3dd5,0xbdfbbcc8,0xbdb53db5,0x3d443ded,0x3dd53d8e,0xbcc83dfb,0x3db53db5,0x3dedbd44,0x3d8ebdd5,0x3dfb3cc8,0x3db5bdb5,0xbd44bded,0xbdd5bd8e,0x3cc8bdfb,
0xbd803d80,0x3dfbbcc8,0x3da2bdc6,0x3de23d71,0xbdedbd44,0x3d8ebdd5,0xbc49bdff,0x3df5bd15,0xbded3d44,0xbcc8bdfb,0xbdc6bda2,0x3d71bde2,0xbd443ded,0xbdd5bd8e,0xbdff3c49,0xbd15bdf5,
0x3d803d80,0xbe000000,0xbdb53db5,0xbdb5bdb5,0xbe00,0xbe000000,0xbdb53db5,0xbdb5bdb5,0xbe00,0xbe000000,0xbdb53db5,0xbdb5bdb5,0xbe00,0xbe000000,0xbdb53db5,0xbdb5bdb5,
0xbd803d80,0x3dfb3cc8,0x3dc6bda2,0x3d713de2,0x3dedbd44,0x3d8e3dd5,0x3dff3c49,0xbd153df5,0x3ded3d44,0xbcc83dfb,0x3da23dc6,0xbde23d71,0x3d443ded,0xbdd53d8e,0xbc493dff,0xbdf5bd15,
0x3d803d80,0xbdedbd44,0xbdd53d8e,0xbcc8bdfb,0x3db53db5,0x3d44bded,0xbd8ebdd5,0x3dfbbcc8,0xbdb53db5,0x3ded3d44,0x3dd5bd8e,0x3cc83dfb,0xbdb5bdb5,0xbd443ded,0x3d8e3dd5,0xbdfb3cc8,
0xbd803d80,0x3dd53d8e,0x3de2bd71,0xbc493dff,0xbd443ded,0xbdfb3cc8,0xbd153df5,0xbda2bdc6,0xbd44bded,0x3d8ebdd5,0xbd71bde2,0x3dff3c49,0x3ded3d44,0x3cc83dfb,0x3df53d15,0xbdc63da2,
0x3d803d80,0xbdb5bdb5,0xbded3d44,0x3d44bded,0xbe000000,0x3db53db5,0x3dedbd44,0xbd443ded,0x3e000000,0xbdb5bdb5,0xbded3d44,0x3d44bded,0xbe000000,0x3db53db5,0x3dedbd44,0xbd443ded,
0xbd803d80,0x3d8e3dd5,0x3df5bd15,0xbda23dc6,0xbd44bded,0x3cc8bdfb,0xbde2bd71,0x3dffbc49,0xbd443ded,0xbdd53d8e,0x3d153df5,0xbdc6bda2,0x3dedbd44,0x3dfb3cc8,0x3d71bde2,0x3c493dff,
0x3d803d80,0xbd44bded,0xbdfb3cc8,0x3dd5bd8e,0x3db5bdb5,0xbded3d44,0x3cc83dfb,0xbd8ebdd5,0xbdb5bdb5,0x3d443ded,0x3dfbbcc8,0xbdd53d8e,0xbdb53db5,0x3dedbd44,0xbcc8bdfb,0x3d8e3dd5,
0xbd803d80,0x3cc83dfb,0x3dffbc49,0xbdf53d15,0x3ded3d44,0x3dd53d8e,0x3da2bdc6,0xbd713de2,0x3dedbd44,0x3dfbbcc8,0xbc49bdff,0x3d153df5,0x3d44bded,0x3d8ebdd5,0xbdc6bda2,0x3de23d71,
0x3d803d80,0xbe00,0xbe000000,0x3e000000,0x3e00,0xbe00,0xbe000000,0x3e000000,0x3e00,0xbe00,0xbe000000,0x3e000000,0x3e00,0xbe00,0xbe000000,0x3e000000,
0xbd803d80,0xbcc83dfb,0x3dff3c49,0xbdf5bd15,0xbded3d44,0xbdd53d8e,0x3da23dc6,0xbd71bde2,0xbdedbd44,0xbdfbbcc8,0xbc493dff,0x3d15bdf5,0xbd44bded,0xbd8ebdd5,0xbdc63da2,0x3de2bd71,
0x3d803d80,0x3d44bded,0xbdfbbcc8,0x3dd53d8e,0xbdb5bdb5,0x3ded3d44,0x3cc8bdfb,0xbd8e3dd5,0x3db5bdb5,0xbd443ded,0x3dfb3cc8,0xbdd5bd8e,0x3db53db5,0xbdedbd44,0xbcc83dfb,0x3d8ebdd5,
0xbd803d80,0xbd8e3dd5,0x3df53d15,0xbda2bdc6,0x3d44bded,0xbcc8bdfb,0xbde23d71,0x3dff3c49,0x3d443ded,0x3dd53d8e,0x3d15bdf5,0xbdc63da2,0xbdedbd44,0xbdfb3cc8,0x3d713de2,0x3c49bdff,
0x3d803d80,0x3db5bdb5,0xbdedbd44,0x3d443ded,0x3e000000,0xbdb53db5,0x3ded3d44,0xbd44bded,0xbe000000,0x3db5bdb5,0xbdedbd44,0x3d443ded,0x3e000000,0xbdb53db5,0x3ded3d44,0xbd44bded,
0xbd803d80,0xbdd53d8e,0x3de23d71,0xbc49bdff,0x3d443ded,0x3dfb3cc8,0xbd15bdf5,0xbda23dc6,0x3d44bded,0xbd8ebdd5,0xbd713de2,0x3dffbc49,0xbded3d44,0xbcc83dfb,0x3df5bd15,0xbdc6bda2,
0x3d803d80,0x3dedbd44,0xbdd5bd8e,0xbcc83dfb,0xbdb53db5,0xbd44bded,0xbd8e3dd5,0x3dfb3cc8,0x3db53db5,0xbded3d44,0x3dd53d8e,0x3cc8bdfb,0x3db5bdb5,0x3d443ded,0x3d8ebdd5,0xbdfbbcc8,
0xbd803d80,0xbdfb3cc8,0x3dc63da2,0x3d71bde2,0xbdedbd44,0xbd8e3dd5,0x3dffbc49,0xbd15bdf5,0xbded3d44,0x3cc83dfb,0x3da2bdc6,0xbde2bd71,0xbd443ded,0x3dd53d8e,0xbc49bdff,0xbdf53d15,
0x3d803d80,0x3e000000,0xbdb5bdb5,0xbdb53db5,0xbe00,0x3e000000,0xbdb5bdb5,0xbdb53db5,0xbe00,0x3e000000,0xbdb5bdb5,0xbdb53db5,0xbe00,0x3e000000,0xbdb5bdb5,0xbdb53db5,
0xbd803d80,0xbdfbbcc8,0x3da23dc6,0x3de2bd71,0x3dedbd44,0xbd8ebdd5,0xbc493dff,0x3df53d15,0x3ded3d44,0x3cc8bdfb,0xbdc63da2,0x3d713de2,0x3d443ded,0x3dd5bd8e,0xbdffbc49,0xbd153df5,
0x3d803d80,0x3ded3d44,0xbd8ebdd5,0xbdfb3cc8,0x3db53db5,0xbd443ded,0x3dd5bd8e,0xbcc8bdfb,0xbdb53db5,0xbdedbd44,0x3d8e3dd5,0x3dfbbcc8,0xbdb5bdb5,0x3d44bded,0xbdd53d8e,0x3cc83dfb,
0xbd803d80,0xbdd5bd8e,0x3d713de2,0x3dff3c49,0xbd443ded,0x3dfbbcc8,0xbdf5bd15,0xbdc63da2,0xbd44bded,0xbd8e3dd5,0x3de2bd71,0x3c49bdff,0x3ded3d44,0xbcc8bdfb,0xbd153df5,0x3da23dc6,
0x3d803d80,0x3db53db5,0xbd44bded,0xbdedbd44,0xbe000000,0xbdb5bdb5,0x3d443ded,0x3ded3d44,0x3e000000,0x3db53db5,0xbd44bded,0xbdedbd44,0xbe000000,0xbdb5bdb5,0x3d443ded,0x3ded3d44,
0xbd803d80,0xbd8ebdd5,0x3d153df5,0x3dc63da2,0xbd44bded,0xbcc83dfb,0x3d71bde2,0xbc49bdff,0xbd443ded,0x3dd5bd8e,0xbdf53d15,0xbda23dc6,0x3dedbd44,0xbdfbbcc8,0x3de23d71,0x3dffbc49,
0x3d803d80,0x3d443ded,0xbcc8bdfb,0xbd8ebdd5,0x3db5bdb5,0x3dedbd44,0xbdfb3cc8,0xbdd53d8e,0xbdb5bdb5,0xbd44bded,0x3cc83dfb,0x3d8e3dd5,0xbdb53db5,0xbded3d44,0x3dfbbcc8,0x3dd5bd8e,
0xbd803d80,0xbcc8bdfb,0x3c493dff,0x3d153df5,0x3ded3d44,0xbdd5bd8e,0x3dc63da2,0x3de23d71,0x3dedbd44,0xbdfb3cc8,0x3dffbc49,0x3df5bd15,0x3d44bded,0xbd8e3dd5,0x3da2bdc6,0x3d71bde2,
0xbc493dff,0xbbc93e00,0xbb493e00,0xbc173dff,0xbcc83dfb,0xbcf93df8,0xbce03dfa,0xbd093df7,0xbd443ded,0xbd5b3de7,0xbd4f3dea,0xbd663de5,0xbd8e3dd5,0xbd983dce,0xbd933dd1,0xbd9d3dca,
0xbd713de2,0xbcf93df8,0xbc7b3dfe,0xbd383def,0xbdd53d8e,0xbdf13d2c,0xbde53d66,0xbdfa3ce0,0xbdedbd44,0xbdcebd98,0xbddfbd7c,0xbdb9bdb1,0xbcc8bdfb,0x3bc9be00,0xbc17bdff,0x3cafbdfc,
0xbdc63da2,0xbd5b3de7,0xbce03dfa,0xbd9d3dca,0xbdfbbcc8,0xbdcebd98,0xbdeabd4f,0xbda7bdc2,0x3d44bded,0x3dbebdac,0x3d93bdd1,0x3ddfbd7c,0x3dd53d8e,0x3d843ddc,0x3db13db9,0x3d213df3,
0xbdf53d15,0xbd983dce,0xbd213df3,0xbdd13d93,0xbd8ebdd5,0x3bc9be00,0xbd09bdf7,0x3d38bdef,0x3ded3d44,0x3d843ddc,0x3dc23da7,0x3ce03dfa,0xbdfb3cc8,0xbde7bd5b,0xbdfebc7b,0xbdb9bdb1,
0xbdffbc49,0xbdbe3dac,0xbd4f3dea,0xbdf33d21,0x3cc8bdfb,0x3ddcbd84,0x3d93bdd1,0x3dfebc7b,0xbd443ded,0xbdf13d2c,0xbdb93db1,0xbdffbc17,0x3d8ebdd5,0x3dfdbc96,0x3dd8bd89,0x3df73d09,
0xbde2bd71,0xbddc3d84,0xbd7c3ddf,0xbe003b49,0x3dd5bd8e,0x3de73d5b,0x3dffbc17,0x3d933dd1,0xbdedbd44,0xbc96bdfd,0xbd9dbdca,0x3d38bdef,0x3cc83dfb,0xbdbe3dac,0xbd213df3,0xbdfa3ce0,
0xbda2bdc6,0xbdf13d2c,0xbd933dd1,0xbdf7bd09,0x3dfb3cc8,0x3c963dfd,0x3db13db9,0xbd663de5,0x3d44bded,0x3e003bc9,0x3dd8bd89,0x3dca3d9d,0xbdd5bd8e,0x3cf9bdf8,0xbd38bdef,0x3dc2bda7,
0xbd15bdf5,0xbdfd3c96,0xbda73dc2,0xbdd8bd89,0x3d8e3dd5,0xbdbe3dac,0xbc7b3dfe,0xbe003b49,0x3ded3d44,0xbcf93df8,0x3d663de5,0xbdd13d93,0x3dfbbcc8,0x3d2c3df1,0x3ddf3d7c,0xbd383def,
0x3c49bdff,0xbe00bbc9,0xbdb93db1,0xbda7bdc2,0xbcc83dfb,0xbdf8bcf9,0xbdd83d89,0xbd7cbddf,0xbd443ded,0xbde7bd5b,0xbdef3d38,0xbd21bdf3,0xbd8e3dd5,0xbdcebd98,0xbdfc3caf,0xbc7bbdfe,
0x3d71bde2,0xbdf8bcf9,0xbdca3d9d,0xbd4fbdea,0xbdd53d8e,0xbd2cbdf1,0xbdf3bd21,0x3d89bdd8,0xbdedbd44,0x3d98bdce,0xbd09bdf7,0x3e00bb49,0xbcc8bdfb,0x3e003bc9,0x3da7bdc2,0x3d933dd1,
0x3dc6bda2,0xbde7bd5b,0xbdd83d89,0xbc7bbdfe,0xbdfbbcc8,0x3d98bdce,0xbd38bdef,0x3dff3c17,0x3d44bded,0x3dac3dbe,0x3dfcbcaf,0xbd093df7,0x3dd53d8e,0xbddc3d84,0xbb493e00,0xbde5bd66,
0x3df5bd15,0xbdcebd98,0xbde53d66,0x3cafbdfc,0xbd8ebdd5,0x3e003bc9,0x3d7cbddf,0x3d4f3dea,0x3ded3d44,0xbddc3d84,0x3c173dff,0xbdd8bd89,0xbdfb3cc8,0x3d5bbde7,0xbd9dbdca,0x3e00bb49,
0x3dff3c49,0xbdacbdbe,0xbdef3d38,0x3d66bde5,0x3cc8bdfb,0x3d843ddc,0x3dfcbcaf,0xbd9d3dca,0xbd443ded,0xbd2cbdf1,0xbe00bb49,0x3dc2bda7,0x3d8ebdd5,0x3c963dfd,0x3dfa3ce0,0xbddf3d7c,
0x3de23d71,0xbd84bddc,0xbdf73d09,0x3db1bdb9,0x3dd5bd8e,0xbd5b3de7,0x3dc23da7,0xbdfcbcaf,0xbdedbd44,0x3dfdbc96,0x3c7bbdfe,0x3d4f3dea,0x3cc83dfb,0xbdacbdbe,0xbde53d66,0x3d89bdd8,
0x3da23dc6,0xbd2cbdf1,0xbdfc3caf,0x3ddfbd7c,0x3dfb3cc8,0xbdfd3c96,0xbb493e00,0xbd21bdf3,0x3d44bded,0xbbc93e00,0x3dfa3ce0,0xbdfe3c7b,0xbdd5bd8e,0x3df83cf9,0x3d4fbdea,0xbc173dff,
0x3d153df5,0xbc96bdfd,0xbdff3c17,0x3dfabce0,0x3d8e3dd5,0xbdacbdbe,0xbdca3d9d,0x3db1bdb9,0x3ded3d44,0xbdf8bcf9,0xbd213df3,0x3cafbdfc,0x3dfbbcc8,0xbdf13d2c,0x3d093df7,0xbd4fbdea,
0xbc493dff,0x3bc9be00,0xbe00bb49,0x3dff3c17,0xbcc83dfb,0x3cf9bdf8,0xbdfabce0,0x3df73d09,0xbd443ded,0x3d5bbde7,0xbdeabd4f,0x3de53d66,0xbd8e3dd5,0x3d98bdce,0xbdd1bd93,0x3dca3d9d,
0xbd713de2,0x3cf9bdf8,0xbdfebc7b,0x3def3d38,0xbdd53d8e,0x3df1bd2c,0xbd66bde5,0x3ce03dfa,0xbdedbd44,0x3dce3d98,0x3d7cbddf,0xbdb13db9,0xbcc8bdfb,0xbbc93e00,0x3dffbc17,0xbdfcbcaf,
0xbdc63da2,0x3d5bbde7,0xbdfabce0,0x3dca3d9d,0xbdfbbcc8,0x3dce3d98,0x3d4fbdea,0xbdc23da7,0x3d44bded,0xbdbe3dac,0x3dd13d93,0xbd7cbddf,0x3dd53d8e,0xbd84bddc,0xbdb93db1,0x3df3bd21,
0xbdf53d15,0x3d98bdce,0xbdf3bd21,0x3d933dd1,0xbd8ebdd5,0xbbc93e00,0x3df7bd09,0xbdefbd38,0x3ded3d44,0xbd84bddc,0xbda73dc2,0x3dfabce0,0xbdfb3cc8,0x3de73d5b,0x3c7bbdfe,0xbdb13db9,
0xbdffbc49,0x3dbebdac,0xbdeabd4f,0x3d213df3,0x3cc8bdfb,0xbddc3d84,0x3dd13d93,0xbc7bbdfe,0xbd443ded,0x3df1bd2c,0xbdb1bdb9,0xbc173dff,0x3d8ebdd5,0xbdfd3c96,0x3d893dd8,0x3d09bdf7,
0xbde2bd71,0x3ddcbd84,0xbddfbd7c,0x3b493e00,0x3dd5bd8e,0xbde7bd5b,0x3c173dff,0x3dd1bd93,0xbdedbd44,0x3c963dfd,0x3dcabd9d,0xbdefbd38,0x3cc83dfb,0x3dbebdac,0xbdf3bd21,0x3ce03dfa,
0xbda2bdc6,0x3df1bd2c,0xbdd1bd93,0xbd093df7,0x3dfb3cc8,0xbc96bdfd,0xbdb93db1,0x3de53d66,0x3d44bded,0xbe00bbc9,0x3d893dd8,0x3d9dbdca,0xbdd5bd8e,0xbcf93df8,0x3defbd38,0xbda7bdc2,
0xbd15bdf5,0x3dfdbc96,0xbdc2bda7,0xbd893dd8,0x3d8e3dd5,0x3dbebdac,0xbdfebc7b,0x3b493e00,0x3ded3d44,0x3cf9bdf8,0xbde53d66,0x3d933dd1,0x3dfbbcc8,0xbd2cbdf1,0xbd7c3ddf,0x3def3d38,
0x3c49bdff,0x3e003bc9,0xbdb1bdb9,0xbdc23da7,0xbcc83dfb,0x3df83cf9,0xbd89bdd8,0xbddf3d7c,0xbd443ded,0x3de73d5b,0xbd38bdef,0xbdf33d21,0xbd8e3dd5,0x3dce3d98,0xbcafbdfc,0xbdfe3c7b,
0x3d71bde2,0x3df83cf9,0xbd9dbdca,0xbdea3d4f,0xbdd53d8e,0x3d2c3df1,0x3d21bdf3,0xbdd8bd89,0xbdedbd44,0xbd983dce,0x3df7bd09,0xbb49be00,0xbcc8bdfb,0xbe00bbc9,0x3dc23da7,0x3dd1bd93,
0x3dc6bda2,0x3de73d5b,0xbd89bdd8,0xbdfe3c7b,0xbdfbbcc8,0xbd983dce,0x3defbd38,0x3c17bdff,0x3d44bded,0xbdacbdbe,0x3caf3dfc,0x3df73d09,0x3dd53d8e,0x3ddcbd84,0xbe00bb49,0xbd663de5,
0x3df5bd15,0x3dce3d98,0xbd66bde5,0xbdfcbcaf,0xbd8ebdd5,0xbe00bbc9,0x3ddf3d7c,0x3deabd4f,0x3ded3d44,0x3ddcbd84,0xbdff3c17,0xbd893dd8,0xbdfb3cc8,0xbd5b3de7,0x3dcabd9d,0xbb49be00,
0x3dff3c49,0x3dac3dbe,0xbd38bdef,0xbde5bd66,0x3cc8bdfb,0xbd84bddc,0x3caf3dfc,0x3dca3d9d,0xbd443ded,0x3d2c3df1,0x3b49be00,0xbda7bdc2,0x3d8ebdd5,0xbc96bdfd,0xbce03dfa,0x3d7c3ddf,
0x3de23d71,0x3d843ddc,0xbd09bdf7,0xbdb9bdb1,0x3dd5bd8e,0x3d5bbde7,0xbda73dc2,0xbcaf3dfc,0xbdedbd44,0xbdfd3c96,0x3dfe3c7b,0x3deabd4f,0x3cc83dfb,0x3dac3dbe,0xbd66bde5,0xbdd8bd89,
0x3da23dc6,0x3d2c3df1,0xbcafbdfc,0xbd7cbddf,0x3dfb3cc8,0x3dfdbc96,0xbe00bb49,0xbdf33d21,0x3d44bded,0x3bc9be00,0xbce03dfa,0x3c7b3dfe,0xbdd5bd8e,0xbdf8bcf9,0x3dea3d4f,0x3dff3c17,
0x3d153df5,0x3c963dfd,0xbc17bdff,0xbce0bdfa,0x3d8e3dd5,0x3dac3dbe,0xbd9dbdca,0xbdb9bdb1,0x3ded3d44,0x3df83cf9,0xbdf3bd21,0xbdfcbcaf,0x3dfbbcc8,0x3df1bd2c,0xbdf73d09,0xbdea3d4f,
0xbdb53d80,0xbdbe3dac,0xbdb93db1,0xbdc23da7,0xbd153df5,0xbddc3d84,0xbdd83d89,0xbddf3d7c,0xbd713de2,0xbdf13d2c,0xbdef3d38,0xbdf33d21,0xbda23dc6,0xbdfd3c96,0xbdfc3caf,0xbdfe3c7b,
0x3db53d80,0x3ddcbd84,0x3dcabd9d,0x3deabd4f,0xbdff3c49,0x3de73d5b,0x3df33d21,0x3dd83d89,0xbda2bdc6,0x3c963dfd,0x3d093df7,0x3b493e00,0x3d15bdf5,0xbdbe3dac,0xbda73dc2,0xbdd13d93,
0xbdb53d80,0xbdf13d2c,0xbdd83d89,0xbdfe3c7b,0xbd71bde2,0xbc96bdfd,0xbd38bdef,0x3c17bdff,0x3df5bd15,0x3e003bc9,0x3dfcbcaf,0x3df73d09,0x3c493dff,0xbcf93df8,0xbb493e00,0xbd663de5,
0x3db53d80,0x3dfdbc96,0x3de5bd66,0x3dfc3caf,0x3da2bdc6,0xbdbe3dac,0xbd7c3ddf,0xbdea3d4f,0xbc493dff,0x3cf9bdf8,0xbc17bdff,0x3d89bdd8,0xbd71bde2,0x3d2c3df1,0x3d9d3dca,0x3b493e00,
0xbdb53d80,0xbe00bbc9,0xbdef3d38,0xbde5bd66,0x3df53d15,0x3df83cf9,0x3dfcbcaf,0x3dca3d9d,0xbde2bd71,0xbde7bd5b,0xbe00bb49,0xbda7bdc2,0x3dc63da2,0x3dce3d98,0x3dfa3ce0,0x3d7c3ddf,
0x3db53d80,0x3df83cf9,0x3df7bd09,0x3db93db1,0x3c493dff,0xbd2cbdf1,0xbdc2bda7,0x3cafbdfc,0x3dc6bda2,0xbd983dce,0xbc7b3dfe,0xbdea3d4f,0xbdf5bd15,0x3e003bc9,0x3de5bd66,0x3dd83d89,
0xbdb53d80,0xbde7bd5b,0xbdfc3caf,0xbd7cbddf,0xbde23d71,0xbd983dce,0xbb493e00,0xbdf33d21,0x3d153df5,0x3dac3dbe,0x3dfa3ce0,0x3c7b3dfe,0x3dffbc49,0x3ddcbd84,0x3d4fbdea,0x3dff3c17,
0x3db53d80,0x3dce3d98,0x3dffbc17,0x3ce03dfa,0xbdc6bda2,0x3e003bc9,0x3dcabd9d,0x3db93db1,0xbdffbc49,0x3ddcbd84,0x3d21bdf3,0x3dfc3caf,0xbde23d71,0x3d5bbde7,0xbd09bdf7,0x3deabd4f,
0xbdb53d80,0xbdacbdbe,0xbe00bb49,0x3c17bdff,0x3d15bdf5,0xbd84bddc,0xbdfabce0,0x3d09bdf7,0x3d71bde2,0xbd2cbdf1,0xbdeabd4f,0x3d66bde5,0x3da2bdc6,0xbc96bdfd,0xbdd1bd93,0x3d9dbdca,
0x3db53d80,0x3d843ddc,0x3dfe3c7b,0xbd383def,0x3dffbc49,0xbd5b3de7,0x3d663de5,0xbdfa3ce0,0x3da23dc6,0xbdfd3c96,0xbd7c3ddf,0xbdb9bdb1,0xbd153df5,0xbdacbdbe,0xbdff3c17,0x3cafbdfc,
0xbdb53d80,0xbd2cbdf1,0xbdfabce0,0x3d9dbdca,0x3d713de2,0x3dfdbc96,0x3d4fbdea,0x3da73dc2,0xbdf53d15,0xbbc93e00,0x3dd13d93,0xbddf3d7c,0xbc49bdff,0xbdf8bcf9,0xbdb93db1,0xbd21bdf3,
0x3db53d80,0x3c963dfd,0x3df33d21,0xbdd13d93,0xbda23dc6,0xbdacbdbe,0xbdf73d09,0x3d38bdef,0x3c49bdff,0x3df83cf9,0x3da7bdc2,0x3ce03dfa,0x3d713de2,0xbdf13d2c,0xbc7b3dfe,0xbdb9bdb1,
0xbdb53d80,0x3bc9be00,0xbdeabd4f,0x3df3bd21,0xbdf5bd15,0xbcf93df8,0x3dd13d93,0xbdfe3c7b,0x3de23d71,0x3d5bbde7,0xbdb1bdb9,0x3dff3c17,0xbdc6bda2,0xbd983dce,0x3d893dd8,0xbdf7bd09,
0x3db53d80,0xbcf93df8,0x3ddf3d7c,0xbe003b49,0xbc49bdff,0x3df1bd2c,0xbc17bdff,0x3d933dd1,0xbdc63da2,0xbdcebd98,0xbdca3d9d,0x3d38bdef,0x3df53d15,0xbbc93e00,0x3df33d21,0xbdfa3ce0,
0xbdb53d80,0x3d5bbde7,0xbdd1bd93,0x3df73d09,0x3de2bd71,0xbdcebd98,0xbdb93db1,0x3d66bde5,0xbd15bdf5,0xbdbe3dac,0x3d893dd8,0xbdcabd9d,0xbdff3c49,0x3d843ddc,0x3defbd38,0xbdc23da7,
0x3db53d80,0xbd983dce,0x3dc23da7,0xbdd8bd89,0x3dc63da2,0xbbc93e00,0x3dfe3c7b,0xbe003b49,0x3dff3c49,0x3d843ddc,0x3de5bd66,0xbdd13d93,0x3de2bd71,0x3de73d5b,0x3d7cbddf,0xbd383def,
0xbdb53d80,0x3dbebdac,0xbdb1bdb9,0x3da73dc2,0xbd153df5,0x3ddcbd84,0xbd89bdd8,0x3d7c3ddf,0xbd713de2,0x3df1bd2c,0xbd38bdef,0x3d213df3,0xbda23dc6,0x3dfdbc96,0xbcafbdfc,0x3c7b3dfe,
0x3db53d80,0xbddc3d84,0x3d9d3dca,0xbd4fbdea,0xbdff3c49,0xbde7bd5b,0xbd213df3,0x3d89bdd8,0xbda2bdc6,0xbc96bdfd,0xbdf73d09,0x3e00bb49,0x3d15bdf5,0x3dbebdac,0xbdc2bda7,0x3d933dd1,
0xbdb53d80,0x3df1bd2c,0xbd89bdd8,0x3c7b3dfe,0xbd71bde2,0x3c963dfd,0x3defbd38,0xbdffbc17,0x3df5bd15,0xbe00bbc9,0x3caf3dfc,0x3d09bdf7,0x3c493dff,0x3cf9bdf8,0xbe00bb49,0x3de53d66,
0x3db53d80,0xbdfd3c96,0x3d663de5,0x3cafbdfc,0x3da2bdc6,0x3dbebdac,0xbddfbd7c,0x3d4f3dea,0xbc493dff,0xbcf93df8,0x3dffbc17,0xbdd8bd89,0xbd71bde2,0xbd2cbdf1,0xbdca3d9d,0x3e00bb49,
0xbdb53d80,0x3e003bc9,0xbd38bdef,0xbd663de5,0x3df53d15,0xbdf8bcf9,0x3caf3dfc,0x3d9dbdca,0xbde2bd71,0x3de73d5b,0x3b49be00,0xbdc23da7,0x3dc63da2,0xbdcebd98,0xbce03dfa,0x3ddfbd7c,
0x3db53d80,0xbdf8bcf9,0x3d093df7,0x3db1bdb9,0x3c493dff,0x3d2c3df1,0x3da7bdc2,0xbdfcbcaf,0x3dc6bda2,0x3d98bdce,0xbdfebc7b,0x3d4f3dea,0xbdf5bd15,0xbe00bbc9,0x3d663de5,0x3d89bdd8,
0xbdb53d80,0x3de73d5b,0xbcafbdfc,0xbddf3d7c,0xbde23d71,0x3d98bdce,0xbe00bb49,0x3d213df3,0x3d153df5,0xbdacbdbe,0xbce03dfa,0x3dfebc7b,0x3dffbc49,0xbddc3d84,0x3dea3d4f,0x3c17bdff,
0x3db53d80,0xbdcebd98,0x3c173dff,0x3dfabce0,0xbdc6bda2,0xbe00bbc9,0x3d9d3dca,0x3db1bdb9,0xbdffbc49,0xbddc3d84,0x3df33d21,0x3cafbdfc,0xbde23d71,0xbd5b3de7,0x3df7bd09,0xbd4fbdea,
0xbdb53d80,0x3dac3dbe,0x3b49be00,0xbdffbc17,0x3d15bdf5,0x3d843ddc,0x3ce0bdfa,0xbdf7bd09,0x3d71bde2,0x3d2c3df1,0x3d4fbdea,0xbde5bd66,0x3da2bdc6,0x3c963dfd,0x3d93bdd1,0xbdcabd9d,
0x3db53d80,0xbd84bddc,0xbc7b3dfe,0x3def3d38,0x3dffbc49,0x3d5bbde7,0xbde53d66,0x3ce03dfa,0x3da23dc6,0x3dfdbc96,0xbddfbd7c,0xbdb13db9,0xbd153df5,0x3dac3dbe,0xbc17bdff,0xbdfcbcaf,
0xbdb53d80,0x3d2c3df1,0x3ce0bdfa,0xbdcabd9d,0x3d713de2,0xbdfd3c96,0x3dea3d4f,0x3dc2bda7,0xbdf53d15,0x3bc9be00,0xbd933dd1,0x3d7c3ddf,0xbc49bdff,0x3df83cf9,0xbdb1bdb9,0xbdf33d21,
0x3db53d80,0xbc96bdfd,0xbd213df3,0x3d933dd1,0xbda23dc6,0x3dac3dbe,0xbd09bdf7,0xbdefbd38,0x3c49bdff,0xbdf8bcf9,0x3dc23da7,0x3dfabce0,0x3d713de2,0x3df1bd2c,0xbdfebc7b,0xbdb13db9,
0xbdb53d80,0xbbc93e00,0x3d4fbdea,0xbd21bdf3,0xbdf5bd15,0x3cf9bdf8,0xbd933dd1,0x3c7b3dfe,0x3de23d71,0xbd5b3de7,0x3db9bdb1,0x3c17bdff,0xbdc6bda2,0x3d98bdce,0xbdd83d89,0xbd093df7,
0x3db53d80,0x3cf9bdf8,0xbd7c3ddf,0x3b493e00,0xbc49bdff,0xbdf13d2c,0x3dffbc17,0x3dd1bd93,0xbdc63da2,0x3dce3d98,0xbd9dbdca,0xbdefbd38,0x3df53d15,0x3bc9be00,0xbd213df3,0x3ce03dfa,
0xbdb53d80,0xbd5b3de7,0x3d93bdd1,0x3d09bdf7,0x3de2bd71,0x3dce3d98,0xbdb1bdb9,0xbde5bd66,0xbd15bdf5,0x3dbebdac,0xbdd83d89,0xbd9d3dca,0xbdff3c49,0xbd84bddc,0x3d383def,0x3da73dc2,
0x3db53d80,0x3d98bdce,0xbda73dc2,0xbd893dd8,0x3dc63da2,0x3bc9be00,0xbc7b3dfe,0x3b493e00,0x3dff3c49,0xbd84bddc,0x3d663de5,0x3d933dd1,0x3de2bd71,0xbde7bd5b,0x3ddf3d7c,0x3def3d38,
0xbcc83dfb,0xbc493dff,0xbbc93e00,0xbc963dfd,0xbd443ded,0xbd713de2,0xbd5b3de7,0xbd843ddc,0xbdb53db5,0xbdc63da2,0xbdbe3dac,0xbdce3d98,0xbded3d44,0xbdf53d15,0xbdf13d2c,0xbdf83cf9,
0xbd8e3dd5,0xbd153df5,0xbc963dfd,0xbd5b3de7,0xbded3d44,0xbdff3c49,0xbdf83cf9,0xbe00bbc9,0xbdb5bdb5,0xbd71bde2,0xbd98bdce,0xbd2cbdf1,0x3d44bded,0x3da2bdc6,0x3d84bddc,0x3dbebdac,
0xbdd53d8e,0xbd713de2,0xbcf93df8,0xbdac3dbe,0xbdedbd44,0xbda2bdc6,0xbdcebd98,0xbd5bbde7,0x3db5bdb5,0x3df5bd15,0x3ddcbd84,0x3e00bbc9,0x3d443ded,0xbc493dff,0x3c963dfd,0xbd2c3df1,
0xbdfb3cc8,0xbda23dc6,0xbd2c3df1,0xbddc3d84,0xbd44bded,0x3d15bdf5,0xbbc9be00,0x3d98bdce,0x3db53db5,0x3c493dff,0x3d5b3de7,0xbcf93df8,0xbdedbd44,0xbd71bde2,0xbdbebdac,0xbc96bdfd,
0xbdfbbcc8,0xbdc63da2,0xbd5b3de7,0xbdf83cf9,0x3d44bded,0x3df5bd15,0x3dbebdac,0x3dfd3c96,0xbdb53db5,0xbdffbc49,0xbdf13d2c,0xbddcbd84,0x3dedbd44,0x3de23d71,0x3e003bc9,0x3d983dce,
0xbdd5bd8e,0xbde23d71,0xbd843ddc,0xbe00bbc9,0x3dedbd44,0x3dc63da2,0x3dfd3c96,0x3d2c3df1,0xbdb5bdb5,0x3d15bdf5,0xbcf9bdf8,0x3dbebdac,0xbd443ded,0xbdff3c49,0xbdce3d98,0xbde7bd5b,
0xbd8ebdd5,0xbdf53d15,0xbd983dce,0xbdf1bd2c,0x3ded3d44,0xbc493dff,0x3d843ddc,0xbdac3dbe,0x3db5bdb5,0x3de23d71,0x3dfdbc96,0x3d5b3de7,0xbd44bded,0x3dc6bda2,0x3cf9bdf8,0x3e00bbc9,
0xbcc8bdfb,0xbdff3c49,0xbdac3dbe,0xbdcebd98,0x3d443ded,0xbde23d71,0xbd2c3df1,0xbdf8bcf9,0x3db53db5,0xbda23dc6,0x3bc93e00,0xbdfd3c96,0x3ded3d44,0xbd153df5,0x3d5b3de7,0xbddc3d84,
0x3cc8bdfb,0xbdffbc49,0xbdbe3dac,0xbd98bdce,0xbd443ded,0xbde2bd71,0xbdf13d2c,0xbcf9bdf8,0xbdb53db5,0xbda2bdc6,0xbe00bbc9,0x3c96bdfd,0xbded3d44,0xbd15bdf5,0xbde7bd5b,0x3d84bddc,
0x3d8ebdd5,0xbdf5bd15,0xbdce3d98,0xbd2cbdf1,0xbded3d44,0xbc49bdff,0xbddcbd84,0x3dbebdac,0xbdb5bdb5,0x3de2bd71,0x3c96bdfd,0x3de73d5b,0x3d44bded,0x3dc63da2,0x3df8bcf9,0xbbc93e00,
0x3dd5bd8e,0xbde2bd71,0xbddc3d84,0xbbc9be00,0xbdedbd44,0x3dc6bda2,0xbc96bdfd,0x3df13d2c,0x3db5bdb5,0x3d153df5,0x3df83cf9,0xbdac3dbe,0x3d443ded,0xbdffbc49,0xbd983dce,0xbd5bbde7,
0x3dfbbcc8,0xbdc6bda2,0xbde73d5b,0x3cf9bdf8,0xbd44bded,0x3df53d15,0x3dacbdbe,0x3c963dfd,0x3db53db5,0xbdff3c49,0xbd2c3df1,0xbd84bddc,0xbdedbd44,0x3de2bd71,0xbbc9be00,0x3dce3d98,
0x3dfb3cc8,0xbda2bdc6,0xbdf13d2c,0x3d84bddc,0x3d44bded,0x3d153df5,0x3e003bc9,0xbdce3d98,0xbdb53db5,0x3c49bdff,0xbde7bd5b,0x3df8bcf9,0x3dedbd44,0xbd713de2,0x3dac3dbe,0xbdfdbc96,
0x3dd53d8e,0xbd71bde2,0xbdf83cf9,0x3dbebdac,0x3dedbd44,0xbda23dc6,0x3d983dce,0xbde7bd5b,0xbdb5bdb5,0x3df53d15,0x3d84bddc,0xbbc93e00,0xbd443ded,0xbc49bdff,0xbdfdbc96,0x3df1bd2c,
0x3d8e3dd5,0xbd15bdf5,0xbdfd3c96,0x3de7bd5b,0x3ded3d44,0xbdffbc49,0xbcf93df8,0xbbc9be00,0x3db5bdb5,0xbd713de2,0x3dce3d98,0xbdf1bd2c,0xbd44bded,0x3da23dc6,0x3ddcbd84,0xbdac3dbe,
0x3cc83dfb,0xbc49bdff,0xbe003bc9,0x3dfdbc96,0x3d443ded,0xbd71bde2,0xbde73d5b,0x3ddcbd84,0x3db53db5,0xbdc6bda2,0xbdac3dbe,0x3d98bdce,0x3ded3d44,0xbdf5bd15,0xbd2c3df1,0x3cf9bdf8,
0xbcc83dfb,0x3c49bdff,0xbe00bbc9,0x3dfd3c96,0xbd443ded,0x3d71bde2,0xbde7bd5b,0x3ddc3d84,0xbdb53db5,0x3dc6bda2,0xbdacbdbe,0x3d983dce,0xbded3d44,0x3df5bd15,0xbd2cbdf1,0x3cf93df8,
0xbd8e3dd5,0x3d15bdf5,0xbdfdbc96,0x3de73d5b,0xbded3d44,0x3dffbc49,0xbcf9bdf8,0xbbc93e00,0xbdb5bdb5,0x3d713de2,0x3dcebd98,0xbdf13d2c,0x3d44bded,0xbda23dc6,0x3ddc3d84,0xbdacbdbe,
0xbdd53d8e,0x3d71bde2,0xbdf8bcf9,0x3dbe3dac,0xbdedbd44,0x3da23dc6,0x3d98bdce,0xbde73d5b,0x3db5bdb5,0xbdf53d15,0x3d843ddc,0xbbc9be00,0x3d443ded,0x3c49bdff,0xbdfd3c96,0x3df13d2c,
0xbdfb3cc8,0x3da2bdc6,0xbdf1bd2c,0x3d843ddc,0xbd44bded,0xbd153df5,0x3e00bbc9,0xbdcebd98,0x3db53db5,0xbc49bdff,0xbde73d5b,0x3df83cf9,0xbdedbd44,0x3d713de2,0x3dacbdbe,0xbdfd3c96,
0xbdfbbcc8,0x3dc6bda2,0xbde7bd5b,0x3cf93df8,0x3d44bded,0xbdf53d15,0x3dac3dbe,0x3c96bdfd,0xbdb53db5,0x3dff3c49,0xbd2cbdf1,0xbd843ddc,0x3dedbd44,0xbde2bd71,0xbbc93e00,0x3dcebd98,
0xbdd5bd8e,0x3de2bd71,0xbddcbd84,0xbbc93e00,0x3dedbd44,0xbdc6bda2,0xbc963dfd,0x3df1bd2c,0xbdb5bdb5,0xbd153df5,0x3df8bcf9,0xbdacbdbe,0xbd443ded,0x3dffbc49,0xbd98bdce,0xbd5b3de7,
0xbd8ebdd5,0x3df5bd15,0xbdcebd98,0xbd2c3df1,0x3ded3d44,0x3c49bdff,0xbddc3d84,0x3dbe3dac,0x3db5bdb5,0xbde2bd71,0x3c963dfd,0x3de7bd5b,0xbd44bded,0xbdc63da2,0x3df83cf9,0xbbc9be00,
0xbcc8bdfb,0x3dffbc49,0xbdbebdac,0xbd983dce,0x3d443ded,0x3de2bd71,0xbdf1bd2c,0xbcf93df8,0x3db53db5,0x3da2bdc6,0xbe003bc9,0x3c963dfd,0x3ded3d44,0x3d15bdf5,0xbde73d5b,0x3d843ddc,
0x3cc8bdfb,0x3dff3c49,0xbdacbdbe,0xbdce3d98,0xbd443ded,0x3de23d71,0xbd2cbdf1,0xbdf83cf9,0xbdb53db5,0x3da23dc6,0x3bc9be00,0xbdfdbc96,0xbded3d44,0x3d153df5,0x3d5bbde7,0xbddcbd84,
0x3d8ebdd5,0x3df53d15,0xbd98bdce,0xbdf13d2c,0xbded3d44,0x3c493dff,0x3d84bddc,0xbdacbdbe,0xbdb5bdb5,0xbde23d71,0x3dfd3c96,0x3d5bbde7,0x3d44bded,0xbdc6bda2,0x3cf93df8,0x3e003bc9,
0x3dd5bd8e,0x3de23d71,0xbd84bddc,0xbe003bc9,0xbdedbd44,0xbdc63da2,0x3dfdbc96,0x3d2cbdf1,0x3db5bdb5,0xbd15bdf5,0xbcf93df8,0x3dbe3dac,0x3d443ded,0x3dff3c49,0xbdcebd98,0xbde73d5b,
0x3dfbbcc8,0x3dc63da2,0xbd5bbde7,0xbdf8bcf9,0xbd44bded,0xbdf5bd15,0x3dbe3dac,0x3dfdbc96,0x3db53db5,0x3dffbc49,0xbdf1bd2c,0xbddc3d84,0xbdedbd44,0xbde23d71,0x3e00bbc9,0x3d98bdce,
0x3dfb3cc8,0x3da23dc6,0xbd2cbdf1,0xbddcbd84,0x3d44bded,0xbd15bdf5,0xbbc93e00,0x3d983dce,0xbdb53db5,0xbc493dff,0x3d5bbde7,0xbcf9bdf8,0x3dedbd44,0x3d71bde2,0xbdbe3dac,0xbc963dfd,
0x3dd53d8e,0x3d713de2,0xbcf9bdf8,0xbdacbdbe,0x3dedbd44,0x3da2bdc6,0xbdce3d98,0xbd5b3de7,0xbdb5bdb5,0xbdf5bd15,0x3ddc3d84,0x3e003bc9,0xbd443ded,0x3c493dff,0x3c96bdfd,0xbd2cbdf1,
0x3d8e3dd5,0x3d153df5,0xbc96bdfd,0xbd5bbde7,0x3ded3d44,0x3dff3c49,0xbdf8bcf9,0xbe003bc9,0x3db5bdb5,0x3d71bde2,0xbd983dce,0xbd2c3df1,0xbd44bded,0xbda2bdc6,0x3d843ddc,0x3dbe3dac,
0x3cc83dfb,0x3c493dff,0xbbc9be00,0xbc96bdfd,0x3d443ded,0x3d713de2,0xbd5bbde7,0xbd84bddc,0x3db53db5,0x3dc63da2,0xbdbebdac,0xbdcebd98,0x3ded3d44,0x3df53d15,0xbdf1bd2c,0xbdf8bcf9,
0xbd803d80,0xbdffbc49,0xbe00bbc9,0xbdfdbc96,0xbd8e3dd5,0xbde2bd71,0xbde7bd5b,0xbddcbd84,0xbdd53d8e,0xbda2bdc6,0xbdacbdbe,0xbd98bdce,0xbdfb3cc8,0xbd15bdf5,0xbd2cbdf1,0xbcf9bdf8,
0x3d803d80,0x3df53d15,0x3dfd3c96,0x3de73d5b,0xbdfbbcc8,0x3c493dff,0x3cf93df8,0xbbc93e00,0xbcc8bdfb,0xbde23d71,0xbdce3d98,0xbdf13d2c,0x3dd5bd8e,0xbdc6bda2,0xbddcbd84,0xbdacbdbe,
0xbd803d80,0xbde2bd71,0xbdf8bcf9,0xbdbebdac,0xbcc8bdfb,0x3dc6bda2,0x3d98bdce,0x3de7bd5b,0x3dfb3cc8,0x3d153df5,0x3d843ddc,0x3bc93e00,0xbd8e3dd5,0xbdffbc49,0xbdfd3c96,0xbdf1bd2c,
0x3d803d80,0x3dc63da2,0x3df13d2c,0x3d843ddc,0x3dd5bd8e,0xbdf5bd15,0xbe003bc9,0xbdcebd98,0xbd8e3dd5,0x3dffbc49,0x3de7bd5b,0x3df83cf9,0x3cc8bdfb,0xbde23d71,0xbdac3dbe,0xbdfd3c96,
0xbd803d80,0xbda2bdc6,0xbde7bd5b,0xbcf9bdf8,0x3dd53d8e,0x3d153df5,0x3dac3dbe,0xbc963dfd,0xbd8ebdd5,0x3c49bdff,0xbd2cbdf1,0x3d84bddc,0x3cc83dfb,0xbd713de2,0xbbc93e00,0xbdce3d98,
0x3d803d80,0x3d713de2,0x3ddc3d84,0xbbc93e00,0xbcc83dfb,0x3da2bdc6,0x3c96bdfd,0x3df1bd2c,0x3dfbbcc8,0xbdf5bd15,0xbdf83cf9,0xbdacbdbe,0xbd8ebdd5,0x3c493dff,0x3d983dce,0xbd5b3de7,
0xbd803d80,0xbd15bdf5,0xbdcebd98,0x3d2cbdf1,0xbdfb3cc8,0xbdffbc49,0xbddc3d84,0xbdbebdac,0xbcc83dfb,0xbd713de2,0x3c963dfd,0xbde73d5b,0x3dd53d8e,0x3da23dc6,0x3df83cf9,0x3bc93e00,
0x3d803d80,0x3c493dff,0x3dbe3dac,0xbd983dce,0xbd8ebdd5,0x3d713de2,0x3df13d2c,0xbcf93df8,0xbdd5bd8e,0x3dc63da2,0x3e00bbc9,0x3c963dfd,0xbdfbbcc8,0x3df53d15,0x3de7bd5b,0x3d843ddc,
0xbd803d80,0x3c49bdff,0xbdacbdbe,0x3dcebd98,0x3d8ebdd5,0x3d71bde2,0xbd2cbdf1,0x3df8bcf9,0x3dd5bd8e,0x3dc6bda2,0x3bc9be00,0x3dfd3c96,0x3dfbbcc8,0x3df5bd15,0x3d5bbde7,0x3ddc3d84,
0x3d803d80,0xbd153df5,0x3d983dce,0xbdf13d2c,0x3dfb3cc8,0xbdff3c49,0xbd843ddc,0xbdacbdbe,0x3cc83dfb,0xbd71bde2,0xbdfdbc96,0x3d5bbde7,0xbdd53d8e,0x3da2bdc6,0xbcf9bdf8,0x3e003bc9,
0xbd803d80,0x3d71bde2,0xbd84bddc,0x3e00bbc9,0x3cc83dfb,0x3da23dc6,0x3dfdbc96,0xbd2c3df1,0xbdfbbcc8,0xbdf53d15,0xbcf93df8,0xbdbebdac,0x3d8ebdd5,0x3c49bdff,0xbdcebd98,0x3de7bd5b,
0x3d803d80,0xbda23dc6,0x3d5b3de7,0xbdf8bcf9,0xbdd53d8e,0x3d15bdf5,0xbdbebdac,0x3dfdbc96,0x3d8ebdd5,0x3c493dff,0x3df13d2c,0xbddc3d84,0xbcc83dfb,0xbd71bde2,0xbe003bc9,0x3d98bdce,
0xbd803d80,0x3dc6bda2,0xbd2cbdf1,0x3ddc3d84,0xbdd5bd8e,0xbdf53d15,0xbbc93e00,0xbd98bdce,0x3d8e3dd5,0x3dff3c49,0x3d5bbde7,0x3cf93df8,0xbcc8bdfb,0xbde2bd71,0xbdbe3dac,0x3c96bdfd,
0x3d803d80,0xbde23d71,0x3cf93df8,0xbdacbdbe,0x3cc8bdfb,0x3dc63da2,0x3dcebd98,0xbd5b3de7,0xbdfb3cc8,0x3d15bdf5,0xbddcbd84,0x3e003bc9,0x3d8e3dd5,0xbdff3c49,0xbc963dfd,0xbd2cbdf1,
0xbd803d80,0x3df5bd15,0xbc96bdfd,0x3d5b3de7,0x3dfbbcc8,0x3c49bdff,0xbdf8bcf9,0x3e00bbc9,0x3cc8bdfb,0xbde2bd71,0xbd983dce,0x3d2cbdf1,0xbdd5bd8e,0xbdc63da2,0x3d843ddc,0xbdbebdac,
0x3d803d80,0xbdff3c49,0x3bc93e00,0xbc96bdfd,0x3d8e3dd5,0xbde23d71,0x3d5b3de7,0xbd84bddc,0x3dd53d8e,0xbda23dc6,0x3dbe3dac,0xbdcebd98,0x3dfb3cc8,0xbd153df5,0x3df13d2c,0xbdf8bcf9,
0xbd803d80,0x3dff3c49,0x3bc9be00,0xbc963dfd,0xbd8e3dd5,0x3de23d71,0x3d5bbde7,0xbd843ddc,0xbdd53d8e,0x3da23dc6,0x3dbebdac,0xbdce3d98,0xbdfb3cc8,0x3d153df5,0x3df1bd2c,0xbdf83cf9,
0x3d803d80,0xbdf5bd15,0xbc963dfd,0x3d5bbde7,0xbdfbbcc8,0xbc49bdff,0xbdf83cf9,0x3e003bc9,0xbcc8bdfb,0x3de2bd71,0xbd98bdce,0x3d2c3df1,0x3dd5bd8e,0x3dc63da2,0x3d84bddc,0xbdbe3dac,
0xbd803d80,0x3de23d71,0x3cf9bdf8,0xbdac3dbe,0xbcc8bdfb,0xbdc63da2,0x3dce3d98,0xbd5bbde7,0x3dfb3cc8,0xbd15bdf5,0xbddc3d84,0x3e00bbc9,0xbd8e3dd5,0x3dff3c49,0xbc96bdfd,0xbd2c3df1,
0x3d803d80,0xbdc6bda2,0xbd2c3df1,0x3ddcbd84,0x3dd5bd8e,0x3df53d15,0xbbc9be00,0xbd983dce,0xbd8e3dd5,0xbdff3c49,0x3d5b3de7,0x3cf9bdf8,0x3cc8bdfb,0x3de2bd71,0xbdbebdac,0x3c963dfd,
0xbd803d80,0x3da23dc6,0x3d5bbde7,0xbdf83cf9,0x3dd53d8e,0xbd15bdf5,0xbdbe3dac,0x3dfd3c96,0xbd8ebdd5,0xbc493dff,0x3df1bd2c,0xbddcbd84,0x3cc83dfb,0x3d71bde2,0xbe00bbc9,0x3d983dce,
0x3d803d80,0xbd71bde2,0xbd843ddc,0x3e003bc9,0xbcc83dfb,0xbda23dc6,0x3dfd3c96,0xbd2cbdf1,0x3dfbbcc8,0x3df53d15,0xbcf9bdf8,0xbdbe3dac,0xbd8ebdd5,0xbc49bdff,0xbdce3d98,0x3de73d5b,
0xbd803d80,0x3d153df5,0x3d98bdce,0xbdf1bd2c,0xbdfb3cc8,0x3dff3c49,0xbd84bddc,0xbdac3dbe,0xbcc83dfb,0x3d71bde2,0xbdfd3c96,0x3d5b3de7,0x3dd53d8e,0xbda2bdc6,0xbcf93df8,0x3e00bbc9,
0x3d803d80,0xbc49bdff,0xbdac3dbe,0x3dce3d98,0xbd8ebdd5,0xbd71bde2,0xbd2c3df1,0x3df83cf9,0xbdd5bd8e,0xbdc6bda2,0x3bc93e00,0x3dfdbc96,0xbdfbbcc8,0xbdf5bd15,0x3d5b3de7,0x3ddcbd84,
0xbd803d80,0xbc493dff,0x3dbebdac,0xbd98bdce,0x3d8ebdd5,0xbd713de2,0x3df1bd2c,0xbcf9bdf8,0x3dd5bd8e,0xbdc63da2,0x3e003bc9,0x3c96bdfd,0x3dfbbcc8,0xbdf53d15,0x3de73d5b,0x3d84bddc,
0x3d803d80,0x3d15bdf5,0xbdce3d98,0x3d2c3df1,0x3dfb3cc8,0x3dffbc49,0xbddcbd84,0xbdbe3dac,0x3cc83dfb,0x3d713de2,0x3c96bdfd,0xbde7bd5b,0xbdd53d8e,0xbda23dc6,0x3df8bcf9,0x3bc9be00,
0xbd803d80,0xbd713de2,0x3ddcbd84,0xbbc9be00,0x3cc83dfb,0xbda2bdc6,0x3c963dfd,0x3df13d2c,0xbdfbbcc8,0x3df5bd15,0xbdf8bcf9,0xbdac3dbe,0x3d8ebdd5,0xbc493dff,0x3d98bdce,0xbd5bbde7,
0x3d803d80,0x3da2bdc6,0xbde73d5b,0xbcf93df8,0xbdd53d8e,0xbd153df5,0x3dacbdbe,0xbc96bdfd,0x3d8ebdd5,0xbc49bdff,0xbd2c3df1,0x3d843ddc,0xbcc83dfb,0x3d713de2,0xbbc9be00,0xbdcebd98,
0xbd803d80,0xbdc63da2,0x3df1bd2c,0x3d84bddc,0xbdd5bd8e,0x3df5bd15,0xbe00bbc9,0xbdce3d98,0x3d8e3dd5,0xbdffbc49,0x3de73d5b,0x3df8bcf9,0xbcc8bdfb,0x3de23d71,0xbdacbdbe,0xbdfdbc96,
0x3d803d80,0x3de2bd71,0xbdf83cf9,0xbdbe3dac,0x3cc8bdfb,0xbdc6bda2,0x3d983dce,0x3de73d5b,0xbdfb3cc8,0xbd153df5,0x3d84bddc,0x3bc9be00,0x3d8e3dd5,0x3dffbc49,0xbdfdbc96,0xbdf13d2c,
0xbd803d80,0xbdf53d15,0x3dfdbc96,0x3de7bd5b,0x3dfbbcc8,0xbc493dff,0x3cf9bdf8,0xbbc9be00,0x3cc8bdfb,0x3de23d71,0xbdcebd98,0xbdf1bd2c,0xbdd5bd8e,0x3dc6bda2,0xbddc3d84,0xbdac3dbe,
0x3d803d80,0x3dffbc49,0xbe003bc9,0xbdfd3c96,0x3d8e3dd5,0x3de2bd71,0xbde73d5b,0xbddc3d84,0x3dd53d8e,0x3da2bdc6,0xbdac3dbe,0xbd983dce,0x3dfb3cc8,0x3d15bdf5,0xbd2c3df1,0xbcf93df8,
0xbd153df5,0xbc963dfd,0xbc173dff,0xbce03dfa,0xbd8e3dd5,0xbdac3dbe,0xbd9d3dca,0xbdb93db1,0xbded3d44,0xbdf83cf9,0xbdf33d21,0xbdfc3caf,0xbdfbbcc8,0xbdf1bd2c,0xbdf7bd09,0xbdeabd4f,
0xbda23dc6,0xbd2c3df1,0xbcaf3dfc,0xbd7c3ddf,0xbdfb3cc8,0xbdfdbc96,0xbe003b49,0xbdf3bd21,0xbd44bded,0xbbc9be00,0xbce0bdfa,0x3c7bbdfe,0x3dd5bd8e,0x3df8bcf9,0x3deabd4f,0x3dffbc17,
0xbde23d71,0xbd843ddc,0xbd093df7,0xbdb93db1,0xbdd5bd8e,0xbd5bbde7,0xbda7bdc2,0xbcafbdfc,0x3dedbd44,0x3dfd3c96,0x3dfebc7b,0x3dea3d4f,0xbcc83dfb,0xbdac3dbe,0xbd663de5,0xbdd83d89,
0xbdff3c49,0xbdac3dbe,0xbd383def,0xbde53d66,0xbcc8bdfb,0x3d84bddc,0x3cafbdfc,0x3dcabd9d,0x3d443ded,0xbd2c3df1,0x3b493e00,0xbda73dc2,0xbd8ebdd5,0x3c96bdfd,0xbce0bdfa,0x3d7cbddf,
0xbdf5bd15,0xbdce3d98,0xbd663de5,0xbdfc3caf,0x3d8ebdd5,0x3e00bbc9,0x3ddfbd7c,0x3dea3d4f,0xbded3d44,0xbddcbd84,0xbdffbc17,0xbd89bdd8,0x3dfb3cc8,0x3d5b3de7,0x3dca3d9d,0xbb493e00,
0xbdc6bda2,0xbde73d5b,0xbd893dd8,0xbdfebc7b,0x3dfbbcc8,0x3d983dce,0x3def3d38,0x3c173dff,0xbd44bded,0x3dacbdbe,0x3cafbdfc,0x3df7bd09,0xbdd53d8e,0xbddcbd84,0xbe003b49,0xbd66bde5,
0xbd71bde2,0xbdf83cf9,0xbd9d3dca,0xbdeabd4f,0x3dd53d8e,0xbd2c3df1,0x3d213df3,0xbdd83d89,0x3dedbd44,0x3d983dce,0x3df73d09,0xbb493e00,0x3cc8bdfb,0x3e00bbc9,0x3dc2bda7,0x3dd13d93,
0xbc49bdff,0xbe003bc9,0xbdb13db9,0xbdc2bda7,0x3cc83dfb,0xbdf83cf9,0xbd893dd8,0xbddfbd7c,0x3d443ded,0xbde73d5b,0xbd383def,0xbdf3bd21,0x3d8e3dd5,0xbdce3d98,0xbcaf3dfc,0xbdfebc7b,
0x3d15bdf5,0xbdfdbc96,0xbdc23da7,0xbd89bdd8,0xbd8e3dd5,0xbdbebdac,0xbdfe3c7b,0x3b49be00,0xbded3d44,0xbcf9bdf8,0xbde5bd66,0x3d93bdd1,0xbdfbbcc8,0x3d2cbdf1,0xbd7cbddf,0x3defbd38,
0x3da2bdc6,0xbdf1bd2c,0xbdd13d93,0xbd09bdf7,0xbdfb3cc8,0x3c96bdfd,0xbdb9bdb1,0x3de5bd66,0xbd44bded,0x3e00bbc9,0x3d89bdd8,0x3d9d3dca,0x3dd5bd8e,0x3cf93df8,0x3def3d38,0xbda73dc2,
0x3de2bd71,0xbddcbd84,0xbddf3d7c,0x3b49be00,0xbdd5bd8e,0x3de7bd5b,0x3c17bdff,0x3dd13d93,0x3dedbd44,0xbc963dfd,0x3dca3d9d,0xbdef3d38,0xbcc83dfb,0xbdbebdac,0xbdf33d21,0x3ce0bdfa,
0x3dffbc49,0xbdbebdac,0xbdea3d4f,0x3d21bdf3,0xbcc8bdfb,0x3ddc3d84,0x3dd1bd93,0xbc7b3dfe,0x3d443ded,0xbdf1bd2c,0xbdb13db9,0xbc17bdff,0xbd8ebdd5,0x3dfd3c96,0x3d89bdd8,0x3d093df7,
0x3df53d15,0xbd98bdce,0xbdf33d21,0x3d93bdd1,0x3d8ebdd5,0x3bc93e00,0x3df73d09,0xbdef3d38,0xbded3d44,0x3d84bddc,0xbda7bdc2,0x3dfa3ce0,0x3dfb3cc8,0xbde73d5b,0x3c7b3dfe,0xbdb1bdb9,
0x3dc63da2,0xbd5bbde7,0xbdfa3ce0,0x3dcabd9d,0x3dfbbcc8,0xbdce3d98,0x3d4f3dea,0xbdc2bda7,0xbd44bded,0x3dbe3dac,0x3dd1bd93,0xbd7c3ddf,0xbdd53d8e,0x3d84bddc,0xbdb9bdb1,0x3df33d21,
0x3d713de2,0xbcf9bdf8,0xbdfe3c7b,0x3defbd38,0x3dd53d8e,0xbdf1bd2c,0xbd663de5,0x3ce0bdfa,0x3dedbd44,0xbdce3d98,0x3d7c3ddf,0xbdb1bdb9,0x3cc8bdfb,0x3bc93e00,0x3dff3c17,0xbdfc3caf,
0x3c493dff,0xbbc9be00,0xbe003b49,0x3dffbc17,0x3cc83dfb,0xbcf9bdf8,0xbdfa3ce0,0x3df7bd09,0x3d443ded,0xbd5bbde7,0xbdea3d4f,0x3de5bd66,0x3d8e3dd5,0xbd98bdce,0xbdd13d93,0x3dcabd9d,
0xbd153df5,0x3c96bdfd,0xbdffbc17,0x3dfa3ce0,0xbd8e3dd5,0x3dacbdbe,0xbdcabd9d,0x3db13db9,0xbded3d44,0x3df8bcf9,0xbd21bdf3,0x3caf3dfc,0xbdfbbcc8,0x3df13d2c,0x3d09bdf7,0xbd4f3dea,
0xbda23dc6,0x3d2cbdf1,0xbdfcbcaf,0x3ddf3d7c,0xbdfb3cc8,0x3dfd3c96,0xbb49be00,0xbd213df3,0xbd44bded,0x3bc93e00,0x3dfabce0,0xbdfebc7b,0x3dd5bd8e,0xbdf83cf9,0x3d4f3dea,0xbc17bdff,
0xbde23d71,0x3d84bddc,0xbdf7bd09,0x3db13db9,0xbdd5bd8e,0x3d5b3de7,0x3dc2bda7,0xbdfc3caf,0x3dedbd44,0xbdfdbc96,0x3c7b3dfe,0x3d4fbdea,0xbcc83dfb,0x3dacbdbe,0xbde5bd66,0x3d893dd8,
0xbdff3c49,0x3dacbdbe,0xbdefbd38,0x3d663de5,0xbcc8bdfb,0xbd843ddc,0x3dfc3caf,0xbd9dbdca,0x3d443ded,0x3d2cbdf1,0xbe003b49,0x3dc23da7,0xbd8ebdd5,0xbc963dfd,0x3dfabce0,0xbddfbd7c,
0xbdf5bd15,0x3dcebd98,0xbde5bd66,0x3caf3dfc,0x3d8ebdd5,0xbe003bc9,0x3d7c3ddf,0x3d4fbdea,0xbded3d44,0x3ddc3d84,0x3c17bdff,0xbdd83d89,0x3dfb3cc8,0xbd5bbde7,0xbd9d3dca,0x3e003b49,
0xbdc6bda2,0x3de7bd5b,0xbdd8bd89,0xbc7b3dfe,0x3dfbbcc8,0xbd98bdce,0xbd383def,0x3dffbc17,0xbd44bded,0xbdac3dbe,0x3dfc3caf,0xbd09bdf7,0xbdd53d8e,0x3ddc3d84,0xbb49be00,0xbde53d66,
0xbd71bde2,0x3df8bcf9,0xbdcabd9d,0xbd4f3dea,0x3dd53d8e,0x3d2cbdf1,0xbdf33d21,0x3d893dd8,0x3dedbd44,0xbd98bdce,0xbd093df7,0x3e003b49,0x3cc8bdfb,0xbe003bc9,0x3da73dc2,0x3d93bdd1,
0xbc49bdff,0x3e00bbc9,0xbdb9bdb1,0xbda73dc2,0x3cc83dfb,0x3df8bcf9,0xbdd8bd89,0xbd7c3ddf,0x3d443ded,0x3de7bd5b,0xbdefbd38,0xbd213df3,0x3d8e3dd5,0x3dcebd98,0xbdfcbcaf,0xbc7b3dfe,
0x3d15bdf5,0x3dfd3c96,0xbda7bdc2,0xbdd83d89,0xbd8e3dd5,0x3dbe3dac,0xbc7bbdfe,0xbe00bb49,0xbded3d44,0x3cf93df8,0x3d66bde5,0xbdd1bd93,0xbdfbbcc8,0xbd2c3df1,0x3ddfbd7c,0xbd38bdef,
0x3da2bdc6,0x3df13d2c,0xbd93bdd1,0xbdf73d09,0xbdfb3cc8,0xbc963dfd,0x3db1bdb9,0xbd66bde5,0xbd44bded,0xbe003bc9,0x3dd83d89,0x3dcabd9d,0x3dd5bd8e,0xbcf9bdf8,0xbd383def,0x3dc23da7,
0x3de2bd71,0x3ddc3d84,0xbd7cbddf,0xbe00bb49,0xbdd5bd8e,0xbde73d5b,0x3dff3c17,0x3d93bdd1,0x3dedbd44,0x3c96bdfd,0xbd9d3dca,0x3d383def,0xbcc83dfb,0x3dbe3dac,0xbd21bdf3,0xbdfabce0,
0x3dffbc49,0x3dbe3dac,0xbd4fbdea,0xbdf3bd21,0xbcc8bdfb,0xbddcbd84,0x3d933dd1,0x3dfe3c7b,0x3d443ded,0x3df13d2c,0xbdb9bdb1,0xbdff3c17,0xbd8ebdd5,0xbdfdbc96,0x3dd83d89,0x3df7bd09,
0x3df53d15,0x3d983dce,0xbd21bdf3,0xbdd1bd93,0x3d8ebdd5,0xbbc9be00,0xbd093df7,0x3d383def,0xbded3d44,0xbd843ddc,0x3dc2bda7,0x3ce0bdfa,0x3dfb3cc8,0x3de7bd5b,0xbdfe3c7b,0xbdb93db1,
0x3dc63da2,0x3d5b3de7,0xbce0bdfa,0xbd9dbdca,0x3dfbbcc8,0x3dcebd98,0xbdea3d4f,0xbda73dc2,0xbd44bded,0xbdbebdac,0x3d933dd1,0x3ddf3d7c,0xbdd53d8e,0xbd843ddc,0x3db1bdb9,0x3d21bdf3,
0x3d713de2,0x3cf93df8,0xbc7bbdfe,0xbd38bdef,0x3dd53d8e,0x3df13d2c,0xbde5bd66,0xbdfabce0,0x3dedbd44,0x3dcebd98,0xbddf3d7c,0xbdb93db1,0x3cc8bdfb,0xbbc9be00,0xbc173dff,0x3caf3dfc,
0x3c493dff,0x3bc93e00,0xbb49be00,0xbc17bdff,0x3cc83dfb,0x3cf93df8,0xbce0bdfa,0xbd09bdf7,0x3d443ded,0x3d5b3de7,0xbd4fbdea,0xbd66bde5,0x3d8e3dd5,0x3d983dce,0xbd93bdd1,0xbd9dbdca,
0xbdb53d80,0xbd98bdce,0xbda7bdc2,0xbd89bdd8,0xbdc63da2,0xbbc9be00,0xbc7bbdfe,0x3b49be00,0xbdff3c49,0x3d84bddc,0x3d66bde5,0x3d93bdd1,0xbde2bd71,0x3de7bd5b,0x3ddfbd7c,0x3defbd38,
0x3db53d80,0x3d5b3de7,0x3d933dd1,0x3d093df7,0xbde2bd71,0xbdce3d98,0xbdb13db9,0xbde53d66,0x3d15bdf5,0xbdbebdac,0xbdd8bd89,0xbd9dbdca,0x3dff3c49,0x3d84bddc,0x3d38bdef,0x3da7bdc2,
0xbdb53d80,0xbcf9bdf8,0xbd7cbddf,0x3b49be00,0x3c49bdff,0x3df13d2c,0x3dff3c17,0x3dd13d93,0x3dc63da2,0xbdce3d98,0xbd9d3dca,0xbdef3d38,0xbdf53d15,0xbbc9be00,0xbd21bdf3,0x3ce0bdfa,
0x3db53d80,0x3bc93e00,0x3d4f3dea,0xbd213df3,0x3df5bd15,0xbcf9bdf8,0xbd93bdd1,0x3c7bbdfe,0xbde23d71,0x3d5b3de7,0x3db93db1,0x3c173dff,0x3dc6bda2,0xbd98bdce,0xbdd8bd89,0xbd09bdf7,
0xbdb53d80,0x3c96bdfd,0xbd21bdf3,0x3d93bdd1,0x3da23dc6,0xbdac3dbe,0xbd093df7,0xbdef3d38,0xbc49bdff,0x3df8bcf9,0x3dc2bda7,0x3dfa3ce0,0xbd713de2,0xbdf1bd2c,0xbdfe3c7b,0xbdb1bdb9,
0x3db53d80,0xbd2c3df1,0x3ce03dfa,0xbdca3d9d,0xbd713de2,0x3dfd3c96,0x3deabd4f,0x3dc23da7,0x3df53d15,0xbbc9be00,0xbd93bdd1,0x3d7cbddf,0x3c49bdff,0xbdf83cf9,0xbdb13db9,0xbdf3bd21,
0xbdb53d80,0x3d84bddc,0xbc7bbdfe,0x3defbd38,0xbdffbc49,0xbd5bbde7,0xbde5bd66,0x3ce0bdfa,0xbda23dc6,0xbdfdbc96,0xbddf3d7c,0xbdb1bdb9,0x3d153df5,0xbdac3dbe,0xbc173dff,0xbdfc3caf,
0x3db53d80,0xbdac3dbe,0x3b493e00,0xbdff3c17,0xbd15bdf5,0xbd843ddc,0x3ce03dfa,0xbdf73d09,0xbd71bde2,0xbd2c3df1,0x3d4f3dea,0xbde53d66,0xbda2bdc6,0xbc963dfd,0x3d933dd1,0xbdca3d9d,
0xbdb53d80,0x3dcebd98,0x3c17bdff,0x3dfa3ce0,0x3dc6bda2,0x3e00bbc9,0x3d9dbdca,0x3db13db9,0x3dffbc49,0x3ddc3d84,0x3df3bd21,0x3caf3dfc,0x3de23d71,0x3d5b3de7,0x3df73d09,0xbd4f3dea,
0x3db53d80,0xbde73d5b,0xbcaf3dfc,0xbddfbd7c,0x3de23d71,0xbd98bdce,0xbe003b49,0x3d21bdf3,0xbd153df5,0x3dacbdbe,0xbce0bdfa,0x3dfe3c7b,0xbdffbc49,0x3ddc3d84,0x3deabd4f,0x3c173dff,
0xbdb53d80,0x3df8bcf9,0x3d09bdf7,0x3db13db9,0xbc493dff,0xbd2c3df1,0x3da73dc2,0xbdfc3caf,0xbdc6bda2,0xbd98bdce,0xbdfe3c7b,0x3d4fbdea,0x3df5bd15,0x3e00bbc9,0x3d66bde5,0x3d893dd8,
0x3db53d80,0xbe003bc9,0xbd383def,0xbd66bde5,0xbdf53d15,0x3df8bcf9,0x3cafbdfc,0x3d9d3dca,0x3de2bd71,0xbde73d5b,0x3b493e00,0xbdc2bda7,0xbdc63da2,0x3dcebd98,0xbce0bdfa,0x3ddf3d7c,
0xbdb53d80,0x3dfd3c96,0x3d66bde5,0x3caf3dfc,0xbda2bdc6,0xbdbebdac,0xbddf3d7c,0x3d4fbdea,0x3c493dff,0x3cf93df8,0x3dff3c17,0xbdd83d89,0x3d71bde2,0x3d2cbdf1,0xbdcabd9d,0x3e003b49,
0x3db53d80,0xbdf1bd2c,0xbd893dd8,0x3c7bbdfe,0x3d71bde2,0xbc963dfd,0x3def3d38,0xbdff3c17,0xbdf5bd15,0x3e00bbc9,0x3cafbdfc,0x3d093df7,0xbc493dff,0xbcf9bdf8,0xbe003b49,0x3de5bd66,
0xbdb53d80,0x3ddc3d84,0x3d9dbdca,0xbd4f3dea,0x3dff3c49,0x3de7bd5b,0xbd21bdf3,0x3d893dd8,0x3da2bdc6,0x3c96bdfd,0xbdf7bd09,0x3e003b49,0xbd15bdf5,0xbdbebdac,0xbdc23da7,0x3d93bdd1,
0x3db53d80,0xbdbebdac,0xbdb13db9,0x3da7bdc2,0x3d153df5,0xbddcbd84,0xbd893dd8,0x3d7cbddf,0x3d713de2,0xbdf1bd2c,0xbd383def,0x3d21bdf3,0x3da23dc6,0xbdfdbc96,0xbcaf3dfc,0x3c7bbdfe,
0xbdb53d80,0x3d983dce,0x3dc2bda7,0xbdd83d89,0xbdc63da2,0x3bc93e00,0x3dfebc7b,0xbe00bb49,0xbdff3c49,0xbd843ddc,0x3de53d66,0xbdd1bd93,0xbde2bd71,0xbde73d5b,0x3d7c3ddf,0xbd38bdef,
0x3db53d80,0xbd5bbde7,0xbdd13d93,0x3df7bd09,0xbde2bd71,0x3dcebd98,0xbdb9bdb1,0x3d663de5,0x3d15bdf5,0x3dbe3dac,0x3d89bdd8,0xbdca3d9d,0x3dff3c49,0xbd843ddc,0x3def3d38,0xbdc2bda7,
0xbdb53d80,0x3cf93df8,0x3ddfbd7c,0xbe00bb49,0x3c49bdff,0xbdf1bd2c,0xbc173dff,0x3d93bdd1,0x3dc63da2,0x3dcebd98,0xbdcabd9d,0x3d383def,0xbdf53d15,0x3bc93e00,0x3df3bd21,0xbdfabce0,
0x3db53d80,0xbbc9be00,0xbdea3d4f,0x3df33d21,0x3df5bd15,0x3cf93df8,0x3dd1bd93,0xbdfebc7b,0xbde23d71,0xbd5bbde7,0xbdb13db9,0x3dffbc17,0x3dc6bda2,0x3d983dce,0x3d89bdd8,0xbdf73d09,
0xbdb53d80,0xbc963dfd,0x3df3bd21,0xbdd1bd93,0x3da23dc6,0x3dacbdbe,0xbdf7bd09,0x3d383def,0xbc49bdff,0xbdf83cf9,0x3da73dc2,0x3ce0bdfa,0xbd713de2,0x3df13d2c,0xbc7bbdfe,0xbdb93db1,
0x3db53d80,0x3d2cbdf1,0xbdfa3ce0,0x3d9d3dca,0xbd713de2,0xbdfdbc96,0x3d4f3dea,0x3da7bdc2,0x3df53d15,0x3bc93e00,0x3dd1bd93,0xbddfbd7c,0x3c49bdff,0x3df8bcf9,0xbdb9bdb1,0xbd213df3,
0xbdb53d80,0xbd843ddc,0x3dfebc7b,0xbd38bdef,0xbdffbc49,0x3d5b3de7,0x3d66bde5,0xbdfabce0,0xbda23dc6,0x3dfd3c96,0xbd7cbddf,0xbdb93db1,0x3d153df5,0x3dacbdbe,0xbdffbc17,0x3caf3dfc,
0x3db53d80,0x3dacbdbe,0xbe003b49,0x3c173dff,0xbd15bdf5,0x3d84bddc,0xbdfa3ce0,0x3d093df7,0xbd71bde2,0x3d2cbdf1,0xbdea3d4f,0x3d663de5,0xbda2bdc6,0x3c96bdfd,0xbdd13d93,0x3d9d3dca,
0xbdb53d80,0xbdce3d98,0x3dff3c17,0x3ce0bdfa,0x3dc6bda2,0xbe003bc9,0x3dca3d9d,0x3db9bdb1,0x3dffbc49,0xbddcbd84,0x3d213df3,0x3dfcbcaf,0x3de23d71,0xbd5bbde7,0xbd093df7,0x3dea3d4f,
0x3db53d80,0x3de7bd5b,0xbdfcbcaf,0xbd7c3ddf,0x3de23d71,0x3d983dce,0xbb49be00,0xbdf3bd21,0xbd153df5,0xbdac3dbe,0x3dfabce0,0x3c7bbdfe,0xbdffbc49,0xbddcbd84,0x3d4f3dea,0x3dffbc17,
0xbdb53d80,0xbdf83cf9,0x3df73d09,0x3db9bdb1,0xbc493dff,0x3d2cbdf1,0xbdc23da7,0x3caf3dfc,0xbdc6bda2,0x3d983dce,0xbc7bbdfe,0xbdeabd4f,0x3df5bd15,0xbe003bc9,0x3de53d66,0x3dd8bd89,
0x3db53d80,0x3e00bbc9,0xbdefbd38,0xbde53d66,0xbdf53d15,0xbdf83cf9,0x3dfc3caf,0x3dcabd9d,0x3de2bd71,0x3de7bd5b,0xbe003b49,0xbda73dc2,0xbdc63da2,0xbdce3d98,0x3dfabce0,0x3d7cbddf,
0xbdb53d80,0xbdfdbc96,0x3de53d66,0x3dfcbcaf,0xbda2bdc6,0x3dbe3dac,0xbd7cbddf,0xbdeabd4f,0x3c493dff,0xbcf9bdf8,0xbc173dff,0x3d893dd8,0x3d71bde2,0xbd2c3df1,0x3d9dbdca,0x3b49be00,
0x3db53d80,0x3df13d2c,0xbdd8bd89,0xbdfebc7b,0x3d71bde2,0x3c96bdfd,0xbd383def,0x3c173dff,0xbdf5bd15,0xbe003bc9,0x3dfc3caf,0x3df7bd09,0xbc493dff,0x3cf93df8,0xbb49be00,0xbd66bde5,
0xbdb53d80,0xbddcbd84,0x3dca3d9d,0x3dea3d4f,0x3dff3c49,0xbde73d5b,0x3df3bd21,0x3dd8bd89,0x3da2bdc6,0xbc963dfd,0x3d09bdf7,0x3b49be00,0xbd15bdf5,0x3dbe3dac,0xbda7bdc2,0xbdd1bd93,
0x3db53d80,0x3dbe3dac,0xbdb9bdb1,0xbdc2bda7,0x3d153df5,0x3ddc3d84,0xbdd8bd89,0xbddfbd7c,0x3d713de2,0x3df13d2c,0xbdefbd38,0xbdf3bd21,0x3da23dc6,0x3dfd3c96,0xbdfcbcaf,0xbdfebc7b,
0x3f800000,0x0,0x3f800000,0x0,0x3f800000,0x0,0x3f800000,0x0,0x3f800000,0x0,0x3f800000,0x0,0x3f800000,0x0,0x3f800000,0x0,
0x3f800000,0x0,0x3f7ffb11,0xbc490e90,0x3f7fec43,0xbcc90ab0,0x3f7fd397,0xbd16c32c,0x3f7fb10f,0xbd48fb30,0x3f7f84ab,0xbd7b2b74,0x3f7f4e6d,0xbd96a905,0x3f7f0e58,0xbdafb680,
0x3f800000,0x0,0x3f7fec43,0xbcc90ab0,0x3f7fb10f,0xbd48fb30,0x3f7f4e6d,0xbd96a905,0x3f7ec46d,0xbdc8bd36,0x3f7e1324,0xbdfab273,0x3f7d3aac,0xbe164083,0x3f7c3b28,0xbe2f10a2,
0x3f800000,0x0,0x3f7fd397,0xbd16c32c,0x3f7f4e6d,0xbd96a905,0x3f7e70b0,0xbde1bc2e,0x3f7d3aac,0xbe164083,0x3f7baccd,0xbe3b6ecf,0x3f79c79d,0xbe605c13,0x3f778bc5,0xbe827dc0,
0x3f800000,0x0,0x3f7fb10f,0xbd48fb30,0x3f7ec46d,0xbdc8bd36,0x3f7d3aac,0xbe164083,0x3f7b14be,0xbe47c5c2,0x3f7853f8,0xbe78cfcc,0x3f74fa0b,0xbe94a031,0x3f710908,0xbeac7cd4,
0x3f800000,0x0,0x3f7f84ab,0xbd7b2b74,0x3f7e1324,0xbdfab273,0x3f7baccd,0xbe3b6ecf,0x3f7853f8,0xbe78cfcc,0x3f740bdd,0xbe9aa086,0x3f6ed89e,0xbeb8442a,0x3f68bf3c,0xbed53641,
0x3f800000,0x0,0x3f7f4e6d,0xbd96a905,0x3f7d3aac,0xbe164083,0x3f79c79d,0xbe605c13,0x3f74fa0b,0xbe94a031,0x3f6ed89e,0xbeb8442a,0x3f676bd8,0xbedae880,0x3f5ebe05,0xbefc5d27,
0x3f800000,0x0,0x3f7f0e58,0xbdafb680,0x3f7c3b28,0xbe2f10a2,0x3f778bc5,0xbe827dc0,0x3f710908,0xbeac7cd4,0x3f68bf3c,0xbed53641,0x3f5ebe05,0xbefc5d27,0x3f531849,0xbf10d3cd,
0x3f800000,0x0,0x3f7b14be,0xbe47c5c2,0x3f6c835e,0xbec3ef15,0x3f54db31,0xbf0e39da,0x3f3504f3,0xbf3504f3,0x3f0e39da,0xbf54db31,0x3ec3ef15,0xbf6c835e,0x3e47c5c2,0xbf7b14be,
0x3f800000,0x0,0x3f7a7302,0xbe541501,0x3f6a09a7,0xbecf7bca,0x3f4f7a1f,0xbf15f6d9,0x3f2beb4a,0xbf3daef9,0x3f00e7e4,0xbf5d2d53,0x3ea09ae5,0xbf731447,0x3de1bc2e,0xbf7e70b0,
0x3f800000,0x0,0x3f79c79d,0xbe605c13,0x3f676bd8,0xbedae880,0x3f49d112,0xbf1d7fd1,0x3f226799,0xbf45e403,0x3ee63375,0xbf64aa59,0x3e78cfcc,0xbf7853f8,0x3cc90ab0,0xbf7fec43,
0x3f800000,0x0,0x3f791298,0xbe6c9a7f,0x3f64aa59,0xbee63375,0x3f43e200,0xbf24d225,0x3f187fc0,0xbf4d9f02,0x3ec9b953,0xbf6b4b0c,0x3e2f10a2,0xbf7c3b28,0xbd7b2b74,0xbf7f84ab,
0x3f800000,0x0,0x3f7853f8,0xbe78cfcc,0x3f61c598,0xbef15aea,0x3f3daef9,0xbf2beb4a,0x3f0e39da,0xbf54db31,0x3eac7cd4,0xbf710908,0x3dc8bd36,0xbf7ec46d,0xbe164083,0xbf7d3aac,
0x3f800000,0x0,0x3f778bc5,0xbe827dc0,0x3f5ebe05,0xbefc5d27,0x3f373a23,0xbf32c8c9,0x3f039c3d,0xbf5b941a,0x3e8e9a22,0xbf75dec6,0x3cc90ab0,0xbf7fec43,0xbe6c9a7f,0xbf791298,
0x3f800000,0x0,0x3f76ba07,0xbe888e93,0x3f5b941a,0xbf039c3d,0x3f3085bb,0xbf396842,0x3ef15aea,0xbf61c598,0x3e605c13,0xbf79c79d,0xbd48fb30,0xbf7fb10f,0xbea09ae5,0xbf731447,
0x3f800000,0x0,0x3f75dec6,0xbe8e9a22,0x3f584853,0xbf08f59b,0x3f299415,0xbf3fc767,0x3edae880,0xbf676bd8,0x3e22abb6,0xbf7cbfc9,0xbdfab273,0xbf7e1324,0xbec9b953,0xbf6b4b0c,
0x3f800000,0x0,0x3f7ec46d,0xbdc8bd36,0x3f7b14be,0xbe47c5c2,0x3f74fa0b,0xbe94a031,0x3f6c835e,0xbec3ef15,0x3f61c598,0xbef15aea,0x3f54db31,0xbf0e39da,0x3f45e403,0xbf226799,
0x3f800000,0x0,0x3f6b4b0c,0xbec9b953,0x3f3085bb,0xbf396842,0x3eb263ef,0xbf6ff573,0xbd48fb30,0xbf7fb10f,0xbee0924f,0xbf660f88,0xbf41d870,0xbf273656,0xbf740bdd,0xbe9aa086,
0x3f800000,0x0,0x3f6a09a7,0xbecf7bca,0x3f2beb4a,0xbf3daef9,0x3ea09ae5,0xbf731447,0xbdc8bd36,0xbf7ec46d,0xbefc5d27,0xbf5ebe05,0xbf4d9f02,0xbf187fc0,0xbf79c79d,0xbe605c13,
0x3f800000,0x0,0x3f68bf3c,0xbed53641,0x3f273656,0xbf41d870,0x3e8e9a22,0xbf75dec6,0xbe164083,0xbf7d3aac,0xbf0b9a6b,0xbf5695e5,0xbf584853,0xbf08f59b,0xbf7dabcc,0xbe09cf86,
0x3f800000,0x0,0x3f676bd8,0xbedae880,0x3f226799,0xbf45e403,0x3e78cfcc,0xbf7853f8,0xbe47c5c2,0xbf7b14be,0xbf187fc0,0xbf4d9f02,0xbf61c598,0xbef15aea,0xbf7fb10f,0xbd48fb30,
0x3f800000,0x0,0x3f660f88,0xbee0924f,0x3f1d7fd1,0xbf49d112,0x3e541501,0xbf7a7302,0xbe78cfcc,0xbf7853f8,0xbf24d225,0xbf43e200,0xbf6a09a7,0xbecf7bca,0xbf7fd397,0x3d16c32c,
0x3f800000,0x0,0x3f64aa59,0xbee63375,0x3f187fc0,0xbf4d9f02,0x3e2f10a2,0xbf7c3b28,0xbe94a031,0xbf74fa0b,0xbf3085bb,0xbf396842,0xbf710908,0xbeac7cd4,0xbf7e1324,0x3dfab273,
0x3f800000,0x0,0x3f633c5a,0xbeebcbbb,0x3f13682a,0xbf514d3d,0x3e09cf86,0xbf7dabcc,0xbeac7cd4,0xbf710908,0xbf3b8f3b,0xbf2e3bde,0xbf76ba07,0xbe888e93,0xbf7a7302,0x3e541501,
0x3f800000,0x0,0x3f74fa0b,0xbe94a031,0x3f54db31,0xbf0e39da,0x3f226799,0xbf45e403,0x3ec3ef15,0xbf6c835e,0x3dc8bd36,0xbf7ec46d,0xbe47c5c2,0xbf7b14be,0xbef15aea,0xbf61c598,
0x3f800000,0x0,0x3f531849,0xbf10d3cd,0x3eb8442a,0xbf6ed89e,0xbe6c9a7f,0xbf791298,0xbf3daef9,0xbf2beb4a,0xbf7dabcc,0xbe09cf86,0xbf64aa59,0x3ee63375,0xbef6e0cb,0x3f604621,
0x3f800000,0x0,0x3f514d3d,0xbf13682a,0x3eac7cd4,0xbf710908,0xbe888e93,0xbf76ba07,0xbf45e403,0xbf226799,0xbf7f4e6d,0xbd96a905,0xbf5b941a,0x3f039c3d,0xbecf7bca,0x3f6a09a7,
0x3f800000,0x0,0x3f4f7a1f,0xbf15f6d9,0x3ea09ae5,0xbf731447,0xbe9aa086,0xbf740bdd,0xbf4d9f02,0xbf187fc0,0xbf7ffb11,0xbc490e90,0xbf514d3d,0x3f13682a,0xbea68f12,0x3f721352,
0x3f800000,0x0,0x3f4d9f02,0xbf187fc0,0x3e94a031,0xbf74fa0b,0xbeac7cd4,0xbf710908,0xbf54db31,0xbf0e39da,0xbf7fb10f,0x3d48fb30,0xbf45e403,0x3f226799,0xbe78cfcc,0x3f7853f8,
0x3f800000,0x0,0x3f4bbbf8,0xbf1b02c6,0x3e888e93,0xbf76ba07,0xbebe1d4a,0xbf6db293,0xbf5b941a,0xbf039c3d,0xbf7e70b0,0x3de1bc2e,0xbf396842,0x3f3085bb,0xbe22abb6,0x3f7cbfc9,
0x3f800000,0x0,0x3f49d112,0xbf1d7fd1,0x3e78cfcc,0xbf7853f8,0xbecf7bca,0xbf6a09a7,0xbf61c598,0xbef15aea,0xbf7c3b28,0x3e2f10a2,0xbf2beb4a,0x3f3daef9,0xbd96a905,0x3f7f4e6d,
0x3f800000,0x0,0x3f47de65,0xbf1ff6cb,0x3e605c13,0xbf79c79d,0xbee0924f,0xbf660f88,0xbf676bd8,0xbedae880,0xbf791298,0x3e6c9a7f,0xbf1d7fd1,0x3f49d112,0x3c490e90,0x3f7ffb11,
0x3f800000,0x0,0x3f800000,0x0,0x3f800000,0x0,0x3f800000,0x0,0x40000000,0x0,0x3f800000,0x0,0x3f800000,0x0,0x3f800000,0x0,
0x3f800000,0x0,0x3f7ffb11,0xbc490e90,0x3f7fec43,0xbcc90ab0,0x3f7fd397,0xbd16c32c,0x3fffb10f,0xbdc8fb30,0x3f7f84ab,0xbd7b2b74,0x3f7f4e6d,0xbd96a905,0x3f7f0e58,0xbdafb680,
0x3f800000,0x0,0x3f7fec43,0xbcc90ab0,0x3f7fb10f,0xbd48fb30,0x3f7f4e6d,0xbd96a905,0x3ffec46d,0xbe48bd36,0x3f7e1324,0xbdfab273,0x3f7d3aac,0xbe164083,0x3f7c3b28,0xbe2f10a2,
0x3f800000,0x0,0x3f7fd397,0xbd16c32c,0x3f7f4e6d,0xbd96a905,0x3f7e70b0,0xbde1bc2e,0x3ffd3aac,0xbe964083,0x3f7baccd,0xbe3b6ecf,0x3f79c79d,0xbe605c13,0x3f778bc5,0xbe827dc0,
0x3f800000,0x0,0x3f7fb10f,0xbd48fb30,0x3f7ec46d,0xbdc8bd36,0x3f7d3aac,0xbe164083,0x3ffb14be,0xbec7c5c2,0x3f7853f8,0xbe78cfcc,0x3f74fa0b,0xbe94a031,0x3f710908,0xbeac7cd4,
0x3f800000,0x0,0x3f7f84ab,0xbd7b2b74,0x3f7e1324,0xbdfab273,0x3f7baccd,0xbe3b6ecf,0x3ff853f8,0xbef8cfcc,0x3f740bdd,0xbe9aa086,0x3f6ed89e,0xbeb8442a,0x3f68bf3c,0xbed53641,
0x3f800000,0x0,0x3f7f4e6d,0xbd96a905,0x3f7d3aac,0xbe164083,0x3f79c79d,0xbe605c13,0x3ff4fa0b,0xbf14a031,0x3f6ed89e,0xbeb8442a,0x3f676bd8,0xbedae880,0x3f5ebe05,0xbefc5d27,
0x3f800000,0x0,0x3f7f0e58,0xbdafb680,0x3f7c3b28,0xbe2f10a2,0x3f778bc5,0xbe827dc0,0x3ff10908,0xbf2c7cd4,0x3f68bf3c,0xbed53641,0x3f5ebe05,0xbefc5d27,0x3f531849,0xbf10d3cd,
0x3f800000,0x0,0x3f7ec46d,0xbdc8bd36,0x3f7b14be,0xbe47c5c2,0x3f74fa0b,0xbe94a031,0x3fec835e,0xbf43ef15,0x3f61c598,0xbef15aea,0x3f54db31,0xbf0e39da,0x3f45e403,0xbf226799,
0x3f800000,0x0,0x3f7e70b0,0xbde1bc2e,0x3f79c79d,0xbe605c13,0x3f721352,0xbea68f12,0x3fe76bd8,0xbf5ae880,0x3f59f26a,0xbf064b82,0x3f49d112,0xbf1d7fd1,0x3f373a23,0xbf32c8c9,
0x3f800000,0x0,0x3f7e1324,0xbdfab273,0x3f7853f8,0xbe78cfcc,0x3f6ed89e,0xbeb8442a,0x3fe1c598,0xbf715aea,0x3f514d3d,0xbf13682a,0x3f3daef9,0xbf2beb4a,0x3f273656,0xbf41d870,
0x3f800000,0x0,0x3f7dabcc,0xbe09cf86,0x3f76ba07,0xbe888e93,0x3f6b4b0c,0xbec9b953,0x3fdb941a,0xbf839c3d,0x3f47de65,0xbf1ff6cb,0x3f3085bb,0xbf396842,0x3f15f6d9,0xbf4f7a1f,
0x3f800000,0x0,0x3f7d3aac,0xbe164083,0x3f74fa0b,0xbe94a031,0x3f676bd8,0xbedae880,0x3fd4db31,0xbf8e39da,0x3f3daef9,0xbf2beb4a,0x3f226799,0xbf45e403,0x3f039c3d,0xbf5b941a,
0x3f800000,0x0,0x3f7cbfc9,0xbe22abb6,0x3f731447,0xbea09ae5,0x3f633c5a,0xbeebcbbb,0x3fcd9f02,0xbf987fc0,0x3f32c8c9,0xbf373a23,0x3f13682a,0xbf514d3d,0x3ee0924f,0xbf660f88,
0x3f800000,0x0,0x3f7c3b28,0xbe2f10a2,0x3f710908,0xbeac7cd4,0x3f5ebe05,0xbefc5d27,0x3fc5e403,0xbfa26799,0x3f273656,0xbf41d870,0x3f039c3d,0xbf5b941a,0x3eb8442a,0xbf6ed89e,
0x3f800000,0x0,0x3f7baccd,0xbe3b6ecf,0x3f6ed89e,0xbeb8442a,0x3f59f26a,0xbf064b82,0x3fbdaef9,0xbfabeb4a,0x3f1b02c6,0xbf4bbbf8,0x3ee63375,0xbf64aa59,0x3e8e9a22,0xbf75dec6,
0x3f800000,0x0,0x3f7b14be,0xbe47c5c2,0x3f6c835e,0xbec3ef15,0x3f54db31,0xbf0e39da,0x3fb504f3,0xbfb504f3,0x3f0e39da,0xbf54db31,0x3ec3ef15,0xbf6c835e,0x3e47c5c2,0xbf7b14be,
0x3f800000,0x0,0x3f7a7302,0xbe541501,0x3f6a09a7,0xbecf7bca,0x3f4f7a1f,0xbf15f6d9,0x3fabeb4a,0xbfbdaef9,0x3f00e7e4,0xbf5d2d53,0x3ea09ae5,0xbf731447,0x3de1bc2e,0xbf7e70b0,
0x3f800000,0x0,0x3f79c79d,0xbe605c13,0x3f676bd8,0xbedae880,0x3f49d112,0xbf1d7fd1,0x3fa26799,0xbfc5e403,0x3ee63375,0xbf64aa59,0x3e78cfcc,0xbf7853f8,0x3cc90ab0,0xbf7fec43,
0x3f800000,0x0,0x3f791298,0xbe6c9a7f,0x3f64aa59,0xbee63375,0x3f43e200,0xbf24d225,0x3f987fc0,0xbfcd9f02,0x3ec9b953,0xbf6b4b0c,0x3e2f10a2,0xbf7c3b28,0xbd7b2b74,0xbf7f84ab,
0x3f800000,0x0,0x3f7853f8,0xbe78cfcc,0x3f61c598,0xbef15aea,0x3f3daef9,0xbf2beb4a,0x3f8e39da,0xbfd4db31,0x3eac7cd4,0xbf710908,0x3dc8bd36,0xbf7ec46d,0xbe164083,0xbf7d3aac,
0x3f800000,0x0,0x3f778bc5,0xbe827dc0,0x3f5ebe05,0xbefc5d27,0x3f373a23,0xbf32c8c9,0x3f839c3d,0xbfdb941a,0x3e8e9a22,0xbf75dec6,0x3cc90ab0,0xbf7fec43,0xbe6c9a7f,0xbf791298,
0x3f800000,0x0,0x3f76ba07,0xbe888e93,0x3f5b941a,0xbf039c3d,0x3f3085bb,0xbf396842,0x3f715aea,0xbfe1c598,0x3e605c13,0xbf79c79d,0xbd48fb30,0xbf7fb10f,0xbea09ae5,0xbf731447,
0x3f800000,0x0,0x3f75dec6,0xbe8e9a22,0x3f584853,0xbf08f59b,0x3f299415,0xbf3fc767,0x3f5ae880,0xbfe76bd8,0x3e22abb6,0xbf7cbfc9,0xbdfab273,0xbf7e1324,0xbec9b953,0xbf6b4b0c,
0x3f800000,0x0,0x3f74fa0b,0xbe94a031,0x3f54db31,0xbf0e39da,0x3f226799,0xbf45e403,0x3f43ef15,0xbfec835e,0x3dc8bd36,0xbf7ec46d,0xbe47c5c2,0xbf7b14be,0xbef15aea,0xbf61c598,
0x3f800000,0x0,0x3f740bdd,0xbe9aa086,0x3f514d3d,0xbf13682a,0x3f1b02c6,0xbf4bbbf8,0x3f2c7cd4,0xbff10908,0x3d16c32c,0xbf7fd397,0xbe888e93,0xbf76ba07,0xbf0b9a6b,0xbf5695e5,
0x3f800000,0x0,0x3f731447,0xbea09ae5,0x3f4d9f02,0xbf187fc0,0x3f13682a,0xbf514d3d,0x3f14a031,0xbff4fa0b,0xbcc90ab0,0xbf7fec43,0xbeac7cd4,0xbf710908,0xbf1d7fd1,0xbf49d112,
0x3f800000,0x0,0x3f721352,0xbea68f12,0x3f49d112,0xbf1d7fd1,0x3f0b9a6b,0xbf5695e5,0x3ef8cfcc,0xbff853f8,0xbdafb680,0xbf7f0e58,0xbecf7bca,0xbf6a09a7,0xbf2e3bde,0xbf3b8f3b,
0x3f800000,0x0,0x3f710908,0xbeac7cd4,0x3f45e403,0xbf226799,0x3f039c3d,0xbf5b941a,0x3ec7c5c2,0xbffb14be,0xbe164083,0xbf7d3aac,0xbef15aea,0xbf61c598,0xbf3daef9,0xbf2beb4a,
0x3f800000,0x0,0x3f6ff573,0xbeb263ef,0x3f41d870,0xbf273656,0x3ef6e0cb,0xbf604621,0x3e964083,0xbffd3aac,0xbe541501,0xbf7a7302,0xbf08f59b,0xbf584853,0xbf4bbbf8,0xbf1b02c6,
0x3f800000,0x0,0x3f6ed89e,0xbeb8442a,0x3f3daef9,0xbf2beb4a,0x3ee63375,0xbf64aa59,0x3e48bd36,0xbffec46d,0xbe888e93,0xbf76ba07,0xbf187fc0,0xbf4d9f02,0xbf584853,0xbf08f59b,
0x3f800000,0x0,0x3f6db293,0xbebe1d4a,0x3f396842,0xbf3085bb,0x3ed53641,0xbf68bf3c,0x3dc8fb30,0xbfffb10f,0xbea68f12,0xbf721352,0xbf273656,0xbf41d870,0xbf633c5a,0xbeebcbbb,
0x3f800000,0x0,0x3f7fffb1,0xbb490fc6,0x3f7ffec4,0xbbc90f88,0x3f7ffd39,0xbc16cb58,0x3ffffb11,0xbcc90e90,0x3f7ff84a,0xbc7b514b,0x3f7ff4e6,0xbc96c9b6,0x3f7ff0e3,0xbcafea69,
0x3f800000,0x0,0x3f7ff84a,0xbc7b514b,0x3f7fe129,0xbcfb49ba,0x3f7fba9e,0xbd3c6dd5,0x3fff84ab,0xbdfb2b74,0x3f7f3f54,0xbd9cecf9,0x3f7eea9d,0xbdbc3ac3,0x3f7e868b,0xbddb7d37,
0x3f800000,0x0,0x3f7fe705,0xbce22a7a,0x3f7f9c18,0xbd621469,0x3f7f1f49,0xbda973ba,0x3ffe70b0,0xbe61bc2e,0x3f7d906e,0xbe0cec4a,0x3f7c7eb0,0xbe28defc,0x3f7b3bab,0xbe44b0b9,
0x3f800000,0x0,0x3f7fcbe2,0xbd2351cb,0x3f7f2f9d,0xbda3308c,0x3f7e2b72,0xbdf475c0,0x3ffcbfc9,0xbea2abb6,0x3f7aed37,0xbe4ada4f,0x3f78b47b,0xbe72b651,0x3f76167a,0xbe8d17c0,
0x3f800000,0x0,0x3f7fa6e3,0xbd55880e,0x3f7e9bc9,0xbdd53db9,0x3f7cdf6c,0xbe1f917b,0x3ffa7302,0xbed41501,0x3f77583a,0xbe840270,0x3f73913f,0xbe9d9e78,0x3f6f20b0,0xbeb6ccc3,
0x3f800000,0x0,0x3f7f7808,0xbd83db0a,0x3f7de0b1,0xbe039502,0x3f7b3bab,0xbe44b0b9,0x3ff78bc5,0xbf027dc0,0x3f72d4eb,0xbea21887,0x3f6d1c1d,0xbec1071e,0x3f666771,0xbedf28a9,
0x3f800000,0x0,0x3f7f3f54,0xbd9cecf9,0x3f7cfe73,0xbe1c76de,0x3f7940c0,0xbe698bba,0x3ff40bdd,0xbf1aa086,0x3f6d67a1,0xbebf926f,0x3f655e0b,0xbee363fa,0x3f5bfb34,0xbf02ef9f,
0x3f800000,0x0,0x3f7efcc9,0xbdb5f8da,0x3f7bf531,0xbe354098,0x3f76ef5b,0xbe870ada,0x3feff573,0xbf3263ef,0x3f671599,0xbedc53c1,0x3f5c61c7,0xbf0242b1,0x3f4fefa8,0xbf1553b7,
0x3f800000,0x0,0x3f7eb069,0xbdcefdb7,0x3f7ac516,0xbe4dee60,0x3f74484b,0xbe9920fe,0x3feb4b0c,0xbf49b953,0x3f5fe4e9,0xbef840c8,0x3f5233c6,0xbf121eb0,0x3f425b89,0xbf269de3,
0x3f800000,0x0,0x3f7e5a38,0xbde7fa9a,0x3f796e4e,0xbe667c66,0x3f714c7a,0xbeab0201,0x3fe60f88,0xbf60924f,0x3f57dc7f,0xbf099f4e,0x3f46e22a,0xbf212ff9,0x3f33587a,0xbf36ad7f,
0x3f800000,0x0,0x3f7dfa38,0xbe007745,0x3f77f110,0xbe7ee6e1,0x3f6dfcf2,0xbebca7af,0x3fe04621,0xbf76e0cb,0x3f4f0417,0xbf16999f,0x3f3a7ca4,0xbf2f61a5,0x3f2302d3,0xbf456439,
0x3f800000,0x0,0x3f7d906e,0xbe0cec4a,0x3f764d97,0xbe8b9507,0x3f6a5ad9,0xbece0bea,0x3fd9f26a,0xbf864b82,0x3f456439,0xbf2302d3,0x3f2d1469,0xbf3ca003,0x3f11796b,0xbf52a649,
0x3f800000,0x0,0x3f7d1cdd,0xbe195be0,0x3f748422,0xbe97a117,0x3f666771,0xbedf28a9,0x3fd31849,0xbf90d3cd,0x3f3b0629,0xbf2ecef7,0x3f1ebc12,0xbf48d8b3,0x3efdbabb,0xbf5e5aa6,
0x3f800000,0x0,0x3f7c9f8a,0xbe25c58c,0x3f7294f8,0xbea395c5,0x3f62241a,0xbeeff7fb,0x3fcbbbf8,0xbf9b02c6,0x3f2ff3e6,0xbf39f2ac,0x3f0f8784,0xbf53fac3,0x3ed6a399,0xbf686b39,
0x3f800000,0x0,0x3f7c187a,0xbe3228d4,0x3f708066,0xbeaf713a,0x3f5d924d,0xbf003a06,0x3fc3e200,0xbfa4d225,0x3f24381a,0xbf446337,0x3eff17b2,0xbf5df6be,0x3eadf73c,0xbf70c501,
0x3f800000,0x0,0x3f7b87b2,0xbe3e853e,0x3f6e46be,0xbebb31a0,0x3f58b3a1,0xbf084b92,0x3fbb8f3b,0xbfae3bde,0x3f17de12,0xbf4e1689,0x3eddbe79,0xbf66becc,0x3e840270,0xbf77583a,
0x3f800000,0x0,0x3f7aed37,0xbe4ada4f,0x3f6be858,0xbec6d529,0x3f5389c7,0xbf102dd5,0x3fb2c8c9,0xbfb73a23,0x3f0af1b7,0xbf570348,0x3ebb31a0,0xbf6e46be,0x3e3228d4,0xbf7c187a,
0x3f800000,0x0,0x3f7a4910,0xbe57278f,0x3f696591,0xbed25a09,0x3f4e1689,0xbf17de12,0x3fa99415,0xbfbfc767,0x3efafef7,0xbf5f20db,0x3e97a117,0xbf748422,0x3db5f8da,0xbf7efcc9,
0x3f800000,0x0,0x3f799b43,0xbe636c83,0x3f66becc,0xbeddbe79,0x3f485bca,0xbf1f599f,0x3f9ff6cb,0xbfc7de65,0x3edf28a9,0xbf666771,0x3e667c66,0xbf796e4e,0x3b490fc6,0xbf7fffb1,
0x3f800000,0x0,0x3f78e3d6,0xbe6fa8b2,0x3f63f473,0xbee900b7,0x3f425b89,0xbf269de3,0x3f95f6d9,0xbfcf7a1f,0x3ec27b55,0xbf6cd007,0x3e1c76de,0xbf7cfe73,0xbda973ba,0xbf7f1f49,
0x3f800000,0x0,0x3f7822d1,0xbe7bdba4,0x3f6106f2,0xbef41f07,0x3f3c17d9,0xbf2da859,0x3f8b9a6b,0xbfd695e5,0x3ea5129f,0xbf725470,0x3da3308c,0xbf7f2f9d,0xbe2bf804,0xbf7c5d3a,
0x3f800000,0x0,0x3f77583a,0xbe840270,0x3f5df6be,0xbeff17b2,0x3f3592e7,0xbf34768f,0x3f80e7e4,0xbfdd2d53,0x3e870ada,0xbf76ef5b,0x3bc90f88,0xbf7ffec4,0xbe80f8c0,0xbf77beb7,
0x3f800000,0x0,0x3f76841b,0xbe8a11f7,0x3f5ac450,0xbf04f484,0x3f2ecef7,0xbf3b0629,0x3f6bcbbb,0xbfe33c5a,0x3e5101f1,0xbf7a9c59,0xbd8a200a,0xbf7f6ac7,0xbeab0201,0xbf714c7a,
0x3f800000,0x0,0x3f75a67b,0xbe901c2c,0x3f577026,0xbf0a48ad,0x3f27ce61,0xbf4154e1,0x3f553641,0xbfe8bf3c,0x3e1324ca,0xbf7d57de,0xbe1008b7,0xbf7d7474,0xbed3c867,0xbf6912ae,
0x3f800000,0x0,0x3f74bf62,0xbe9620d2,0x3f53fac3,0xbf0f8784,0x3f209393,0xbf476085,0x3f3e1d4a,0xbfedb293,0x3da973ba,0xbf7f1f49,0xbe5a3997,0xbf7a1e84,0xbefafef7,0xbf5f20db,
0x3f800000,0x0,0x3f73ced9,0xbe9c1faf,0x3f5064af,0xbf14b039,0x3f19210f,0xbf4d26fd,0x3f268f12,0xbff21352,0x3cafea69,0xbf7ff0e3,0xbe919ddd,0xbf756d97,0xbf102dd5,0xbf5389c7,
0x3f800000,0x0,0x3f72d4eb,0xbea21887,0x3f4cae79,0xbf19c200,0x3f11796b,0xbf52a649,0x3f0e9a22,0xbff5dec6,0xbd2351cb,0xbf7fcbe2,0xbeb554ec,0xbf6f6830,0xbf21cbfb,0xbf466354,
0x3f800000,0x0,0x3f71d19f,0xbea80b1f,0x3f48d8b3,0xbf1ebc12,0x3f099f4e,0xbf57dc7f,0x3eec9a7f,0xbff91298,0xbdcefdb7,0xbf7eb069,0xbed8106b,0xbf6816a8,0xbf3238aa,0xbf37c655,
0x3f800000,0x0,0x3f70c501,0xbeadf73c,0x3f44e3f5,0xbf239da9,0x3f019573,0xbf5cc7d1,0x3ebb6ecf,0xbffbaccd,0xbe25c58c,0xbf7c9f8a,0xbef9a02d,0xbf5f8327,0xbf4154e1,0xbf27ce61,
0x3f800000,0x0,0x3f6faf1b,0xbeb3dca5,0x3f40d0da,0xbf286605,0x3ef2bd43,0xbf61668a,0x3e89cf86,0xbffdabcc,0xbe636c83,0xbf799b43,0xbf0cead0,0xbf55b993,0xbf4f0417,0xbf16999f,
0x3f800000,0x0,0x3f6e8ff8,0xbeb9bb1e,0x3f3ca003,0xbf2d1469,0x3ee1fb6a,0xbf65b710,0x3e2fb680,0xbfff0e58,0xbe901c2c,0xbf75a67b,0xbf1c420c,0xbf4ac77f,0xbf5b2c79,0xbf044889,
0x3f800000,0x0,0x3f6d67a1,0xbebf926f,0x3f385216,0xbf31a81d,0x3ed0eb2a,0xbf69b7e4,0x3d96c32c,0xbfffd397,0xbeadf73c,0xbf70c501,0xbf2ac082,0xbf3ebc1b,0xbf65b710,0xbee1fb6a,
0x3f800000,0x0,0x3f7ffec4,0xbbc90f88,0x3f7ffb11,0xbc490e90,0x3f7ff4e6,0xbc96c9b6,0x3fffec43,0xbd490ab0,0x3f7fe129,0xbcfb49ba,0x3f7fd397,0xbd16c32c,0x3f7fc38f,0xbd2fe007,
0x3f800000,0x0,0x3f7ff4e6,0xbc96c9b6,0x3f7fd397,0xbd16c32c,0x3f7f9c18,0xbd621469,0x3fff4e6d,0xbe16a905,0x3f7eea9d,0xbdbc3ac3,0x3f7e70b0,0xbde1bc2e,0x3f7de0b1,0xbe039502,
0x3f800000,0x0,0x3f7fe129,0xbcfb49ba,0x3f7f84ab,0xbd7b2b74,0x3f7eea9d,0xbdbc3ac3,0x3ffe1324,0xbe7ab273,0x3f7cfe73,0xbe1c76de,0x3f7baccd,0xbe3b6ecf,0x3f7a1e84,0xbe5a3997,
0x3f800000,0x0,0x3f7fc38f,0xbd2fe007,0x3f7f0e58,0xbdafb680,0x3f7de0b1,0xbe039502,0x3ffc3b28,0xbeaf10a2,0x3f7a1e84,0xbe5a3997,0x3f778bc5,0xbe827dc0,0x3f748422,0xbe97a117,
0x3f800000,0x0,0x3f7f9c18,0xbd621469,0x3f7e70b0,0xbde1bc2e,0x3f7c7eb0,0xbe28defc,0x3ff9c79d,0xbee05c13,0x3f764d97,0xbe8b9507,0x3f721352,0xbea68f12,0x3f6d1c1d,0xbec1071e,
0x3f800000,0x0,0x3f7f6ac7,0xbd8a200a,0x3f7dabcc,0xbe09cf86,0x3f7ac516,0xbe4dee60,0x3ff6ba07,0xbf088e93,0x3f718f57,0xbea986c4,0x3f6b4b0c,0xbec9b953,0x3f63f473,0xbee900b7,
0x3f800000,0x0,0x3f7f2f9d,0xbda3308c,0x3f7cbfc9,0xbe22abb6,0x3f78b47b,0xbe72b651,0x3ff31447,0xbf209ae5,0x3f6be858,0xbec6d529,0x3f633c5a,0xbeebcbbb,0x3f591e6a,0xbf07a136,
0x3f800000,0x0,0x3f7eea9d,0xbdbc3ac3,0x3f7baccd,0xbe3b6ecf,0x3f764d97,0xbe8b9507,0x3feed89e,0xbf38442a,0x3f655e0b,0xbee363fa,0x3f59f26a,0xbf064b82,0x3f4cae79,0xbf19c200,
0x3f800000,0x0,0x3f7e9bc9,0xbdd53db9,0x3f7a7302,0xbe541501,0x3f73913f,0xbe9d9e78,0x3fea09a7,0xbf4f7bca,0x3f5df6be,0xbeff17b2,0x3f4f7a1f,0xbf15f6d9,0x3f3ebc1b,0xbf2ac082,
0x3f800000,0x0,0x3f7e4323,0xbdee3876,0x3f791298,0xbe6c9a7f,0x3f708066,0xbeaf713a,0x3fe4aa59,0xbf663375,0x3f55b993,0xbf0cead0,0x3f43e200,0xbf24d225,0x3f2f61a5,0xbf3a7ca4,
0x3f800000,0x0,0x3f7de0b1,0xbe039502,0x3f778bc5,0xbe827dc0,0x3f6d1c1d,0xbec1071e,0x3fdebe05,0xbf7c5d27,0x3f4cae79,0xbf19c200,0x3f373a23,0xbf32c8c9,0x3f1ebc12,0xbf48d8b3,
0x3f800000,0x0,0x3f7d7474,0xbe1008b7,0x3f75dec6,0xbe8e9a22,0x3f696591,0xbed25a09,0x3fd84853,0xbf88f59b,0x3f42de29,0xbf26050a,0x3f299415,0xbf3fc767,0x3f0cead0,0xbf55b993,
0x3f800000,0x0,0x3f7cfe73,0xbe1c76de,0x3f740bdd,0xbe9aa086,0x3f655e0b,0xbee363fa,0x3fd14d3d,0xbf93682a,0x3f385216,0xbf31a81d,0x3f1b02c6,0xbf4bbbf8,0x3ef41f07,0xbf6106f2,
0x3f800000,0x0,0x3f7c7eb0,0xbe28defc,0x3f721352,0xbea68f12,0x3f6106f2,0xbef41f07,0x3fc9d112,0xbf9d7fd1,0x3f2d1469,0xbf3ca003,0x3f0b9a6b,0xbf5695e5,0x3ecc9b8b,0xbf6aab7b,
0x3f800000,0x0,0x3f7bf531,0xbe354098,0x3f6ff573,0xbeb263ef,0x3f5c61c7,0xbf0242b1,0x3fc1d870,0xbfa73656,0x3f212ff9,0xbf46e22a,0x3ef6e0cb,0xbf604621,0x3ea395c5,0xbf7294f8,
0x3f800000,0x0,0x3f7b61fc,0xbe419b37,0x3f6db293,0xbebe1d4a,0x3f577026,0xbf0a48ad,0x3fb96842,0xbfb085bb,0x3f14b039,0xbf5064af,0x3ed53641,0xbf68bf3c,0x3e72b651,0xbf78b47b,
0x3f800000,0x0,0x3f7ac516,0xbe4dee60,0x3f6b4b0c,0xbec9b953,0x3f5233c6,0xbf121eb0,0x3fb085bb,0xbfb96842,0x3f07a136,0xbf591e6a,0x3eb263ef,0xbf6ff573,0x3e1c76de,0xbf7cfe73,
0x3f800000,0x0,0x3f7a1e84,0xbe5a3997,0x3f68bf3c,0xbed53641,0x3f4cae79,0xbf19c200,0x3fa73656,0xbfc1d870,0x3ef41f07,0xbf6106f2,0x3e8e9a22,0xbf75dec6,0x3d8a200a,0xbf7f6ac7,
0x3f800000,0x0,0x3f796e4e,0xbe667c66,0x3f660f88,0xbee0924f,0x3f46e22a,0xbf212ff9,0x3f9d7fd1,0xbfc9d112,0x3ed8106b,0xbf6816a8,0x3e541501,0xbf7a7302,0xbc96c9b6,0xbf7ff4e6,
0x3f800000,0x0,0x3f78b47b,0xbe72b651,0x3f633c5a,0xbeebcbbb,0x3f40d0da,0xbf286605,0x3f93682a,0xbfd14d3d,0x3ebb31a0,0xbf6e46be,0x3e09cf86,0xbf7dabcc,0xbdd53db9,0xbf7e9bc9,
0x3f800000,0x0,0x3f77f110,0xbe7ee6e1,0x3f604621,0xbef6e0cb,0x3f3a7ca4,0xbf2f61a5,0x3f88f59b,0xbfd84853,0x3e9d9e78,0xbf73913f,0x3d7b2b74,0xbf7f84ab,0xbe419b37,0xbf7b61fc,
0x3f800000,0x0,0x3f772417,0xbe8586ce,0x3f5d2d53,0xbf00e7e4,0x3f33e7bc,0xbf36206c,0x3f7c5d27,0xbfdebe05,0x3e7ee6e1,0xbf77f110,0xbc490e90,0xbf7ffb11,0xbe8b9507,0xbf764d97,
0x3f800000,0x0,0x3f764d97,0xbe8b9507,0x3f59f26a,0xbf064b82,0x3f2d1469,0xbf3ca003,0x3f663375,0xbfe4aa59,0x3e419b37,0xbf7b61fc,0xbdafb680,0xbf7f0e58,0xbeb554ec,0xbf6f6830,
0x3f800000,0x0,0x3f756d97,0xbe919ddd,0x3f5695e5,0xbf0b9a6b,0x3f26050a,0xbf42de29,0x3f4f7bca,0xbfea09a7,0x3e039502,0xbf7de0b1,0xbe22abb6,0xbf7cbfc9,0xbeddbe79,0xbf66becc,
0x3f800000,0x0,0x3f748422,0xbe97a117,0x3f531849,0xbf10d3cd,0x3f1ebc12,0xbf48d8b3,0x3f38442a,0xbfeed89e,0x3d8a200a,0xbf7f6ac7,0xbe6c9a7f,0xbf791298,0xbf0242b1,0xbf5c61c7,
0x3f800000,0x0,0x3f73913f,0xbe9d9e78,0x3f4f7a1f,0xbf15f6d9,0x3f173c07,0xbf4e8d90,0x3f209ae5,0xbff31447,0x3bc90f88,0xbf7ffec4,0xbe9aa086,0xbf740bdd,0xbf14b039,0xbf5064af,
0x3f800000,0x0,0x3f7294f8,0xbea395c5,0x3f4bbbf8,0xbf1b02c6,0x3f0f8784,0xbf53fac3,0x3f088e93,0xbff6ba07,0xbd621469,0xbf7f9c18,0xbebe1d4a,0xbf6db293,0xbf26050a,0xbf42de29,
0x3f800000,0x0,0x3f718f57,0xbea986c4,0x3f47de65,0xbf1ff6cb,0x3f07a136,0xbf591e6a,0x3ee05c13,0xbff9c79d,0xbdee3876,0xbf7e4323,0xbee0924f,0xbf660f88,0xbf36206c,0xbf33e7bc,
0x3f800000,0x0,0x3f708066,0xbeaf713a,0x3f43e200,0xbf24d225,0x3eff17b2,0xbf5df6be,0x3eaf10a2,0xbffc3b28,0xbe354098,0xbf7bf531,0xbf00e7e4,0xbf5d2d53,0xbf44e3f5,0xbf239da9,
0x3f800000,0x0,0x3f6f6830,0xbeb554ec,0x3f3fc767,0xbf299415,0x3eee9479,0xbf628210,0x3e7ab273,0xbffe1324,0xbe72b651,0xbf78b47b,0xbf10d3cd,0xbf531849,0xbf5233c6,0xbf121eb0,
0x3f800000,0x0,0x3f6e46be,0xbebb31a0,0x3f3b8f3b,0xbf2e3bde,0x3eddbe79,0xbf66becc,0x3e16a905,0xbfff4e6d,0xbe97a117,0xbf748422,0xbf1ff6cb,0xbf47de65,0xbf5df6be,0xbeff17b2,
0x3f800000,0x0,0x3f6d1c1d,0xbec1071e,0x3f373a23,0xbf32c8c9,0x3ecc9b8b,0xbf6aab7b,0x3d490ab0,0xbfffec43,0xbeb554ec,0xbf6f6830,0xbf2e3bde,0xbf3b8f3b,0xbf6816a8,0xbed8106b,
0x3f800000,0x0,0x3f7ffd39,0xbc16cb58,0x3f7ff4e6,0xbc96c9b6,0x3f7fe705,0xbce22a7a,0x3fffd397,0xbd96c32c,0x3f7fba9e,0xbd3c6dd5,0x3f7f9c18,0xbd621469,0x3f7f7808,0xbd83db0a,
0x3f800000,0x0,0x3f7ff0e3,0xbcafea69,0x3f7fc38f,0xbd2fe007,0x3f7f7808,0xbd83db0a,0x3fff0e58,0xbe2fb680,0x3f7e868b,0xbddb7d37,0x3f7de0b1,0xbe039502,0x3f7d1cdd,0xbe195be0,
0x3f800000,0x0,0x3f7fdaaf,0xbd0a342f,0x3f7f6ac7,0xbd8a200a,0x3f7eb069,0xbdcefdb7,0x3ffdabcc,0xbe89cf86,0x3f7c5d3a,0xbe2bf804,0x3f7ac516,0xbe4dee60,0x3f78e3d6,0xbe6fa8b2,
0x3f800000,0x0,0x3f7fba9e,0xbd3c6dd5,0x3f7eea9d,0xbdbc3ac3,0x3f7d906e,0xbe0cec4a,0x3ffbaccd,0xbebb6ecf,0x3f7940c0,0xbe698bba,0x3f764d97,0xbe8b9507,0x3f72d4eb,0xbea21887,
0x3f800000,0x0,0x3f7f90b1,0xbd6ea038,0x3f7e4323,0xbdee3876,0x3f7c187a,0xbe3228d4,0x3ff91298,0xbeec9a7f,0x3f75341d,0xbe931f35,0x3f708066,0xbeaf713a,0x3f6afb8c,0xbecb2aae,
0x3f800000,0x0,0x3f7f5ce9,0xbd9064b4,0x3f7d7474,0xbe1008b7,0x3f7a4910,0xbe57278f,0x3ff5dec6,0xbf0e9a22,0x3f703b37,0xbeb0eacb,0x3f696591,0xbed25a09,0x3f61668a,0xbef2bd43,
0x3f800000,0x0,0x3f7f1f49,0xbda973ba,0x3f7c7eb0,0xbe28defc,0x3f7822d1,0xbe7bdba4,0x3ff21352,0xbf268f12,0x3f6a5ad9,0xbece0bea,0x3f6106f2,0xbef41f07,0x3f5627fe,0xbf0c42c9,
0x3f800000,0x0,0x3f7ed7d4,0xbdc27c39,0x3f7b61fc,0xbe419b37,0x3f75a67b,0xbe901c2c,0x3fedb293,0xbf3e1d4a,0x3f6398ac,0xbeea6681,0x3f577026,0xbf0a48ad,0x3f495521,0xbf1e1e22,
0x3f800000,0x0,0x3f7e868b,0xbddb7d37,0x3f7a1e84,0xbe5a3997,0x3f72d4eb,0xbea21887,0x3fe8bf3c,0xbf553641,0x3f5bfb34,0xbf02ef9f,0x3f4cae79,0xbf19c200,0x3f3b0629,0xbf2ecef7,
0x3f800000,0x0,0x3f7e2b72,0xbdf475c0,0x3f78b47b,0xbe72b651,0x3f6faf1b,0xbeb3dca5,0x3fe33c5a,0xbf6bcbbb,0x3f5389c7,0xbf102dd5,0x3f40d0da,0xbf286605,0x3f2b561b,0xbf3e35c5,
0x3f800000,0x0,0x3f7dc68c,0xbe06b26e,0x3f772417,0xbe8586ce,0x3f6c3624,0xbec5625c,0x3fdd2d53,0xbf80e7e4,0x3f4a4c87,0xbf1ce11f,0x3f33e7bc,0xbf36206c,0x3f1a6293,0xbf4c3578,
0x3f800000,0x0,0x3f7d57de,0xbe1324ca,0x3f756d97,0xbe919ddd,0x3f686b39,0xbed6a399,0x3fd695e5,0xbf8b9a6b,0x3f404c5c,0xbf28fd41,0x3f26050a,0xbf42de29,0x3f084b92,0xbf58b3a1,
0x3f800000,0x0,0x3f7cdf6c,0xbe1f917b,0x3f73913f,0xbe9d9e78,0x3f644fac,0xbee79a5d,0x3fcf7a1f,0xbf95f6d9,0x3f3592e7,0xbf34768f,0x3f173c07,0xbf4e8d90,0x3eea6681,0xbf6398ac,
0x3f800000,0x0,0x3f7c5d3a,0xbe2bf804,0x3f718f57,0xbea986c4,0x3f5fe4e9,0xbef840c8,0x3fc7de65,0xbf9ff6cb,0x3f2a2a80,0xbf3f41fc,0x3f07a136,0xbf591e6a,0x3ec27b55,0xbf6cd007,
0x3f800000,0x0,0x3f7bd14d,0xbe3857ec,0x3f6f6830,0xbeb554ec,0x3f5b2c79,0xbf044889,0x3fbfc767,0xbfa99415,0x3f1e1e22,0xbf495521,0x3eee9479,0xbf628210,0x3e9920fe,0xbf74484b,
0x3f800000,0x0,0x3f7b3bab,0xbe44b0b9,0x3f6d1c1d,0xbec1071e,0x3f5627fe,0xbf0c42c9,0x3fb73a23,0xbfb2c8c9,0x3f11796b,0xbf52a649,0x3ecc9b8b,0xbf6aab7b,0x3e5d4b1a,0xbf79f35e,
0x3f800000,0x0,0x3f7a9c59,0xbe5101f1,0x3f6aab7b,0xbecc9b8b,0x3f50d937,0xbf140c5f,0x3fae3bde,0xbfbb8f3b,0x3f044889,0xbf5b2c79,0x3ea986c4,0xbf718f57,0x3e06b26e,0xbf7dc68c,
0x3f800000,0x0,0x3f79f35e,0xbe5d4b1a,0x3f6816a8,0xbed8106b,0x3f4b41fa,0xbf1ba299,0x3fa4d225,0xbfc3e200,0x3eed3063,0xbf62df7b,0x3e8586ce,0xbf772417,0x3d3c6dd5,0xbf7fba9e,
0x3f800000,0x0,0x3f7940c0,0xbe698bba,0x3f655e0b,0xbee363fa,0x3f456439,0xbf2302d3,0x3f9b02c6,0xbfcbbbf8,0x3ed0eb2a,0xbf69b7e4,0x3e419b37,0xbf7b61fc,0xbd2351cb,0xbf7fcbe2,
0x3f800000,0x0,0x3f788486,0xbe75c35a,0x3f628210,0xbeee9479,0x3f3f41fc,0xbf2a2a80,0x3f90d3cd,0xbfd31849,0x3eb3dca5,0xbf6faf1b,0x3dee3876,0xbf7e4323,0xbe007745,0xbf7dfa38,
0x3f800000,0x0,0x3f77beb7,0xbe80f8c0,0x3f5f8327,0xbef9a02d,0x3f38dd65,0xbf311722,0x3f864b82,0xbfd9f26a,0x3e9620d2,0xbf74bf62,0x3d2fe007,0xbf7fc38f,0xbe57278f,0xbf7a4910,
0x3f800000,0x0,0x3f76ef5b,0xbe870ada,0x3f5c61c7,0xbf0242b1,0x3f3238aa,0xbf37c655,0x3f76e0cb,0xbfe04621,0x3e6fa8b2,0xbf78e3d6,0xbcfb49ba,0xbf7fe129,0xbe9620d2,0xbf74bf62,
0x3f800000,0x0,0x3f76167a,0xbe8d17c0,0x3f591e6a,0xbf07a136,0x3f2b561b,0xbf3e35c5,0x3f60924f,0xbfe60f88,0x3e3228d4,0xbf7c187a,0xbdd53db9,0xbf7e9bc9,0xbebf926f,0xbf6d67a1,
0x3f800000,0x0,0x3f75341d,0xbe931f35,0x3f55b993,0xbf0cead0,0x3f24381a,0xbf446337,0x3f49b953,0xbfeb4b0c,0x3de7fa9a,0xbf7e5a38,0xbe354098,0xbf7bf531,0xbee79a5d,0xbf644fac,
0x3f800000,0x0,0x3f74484b,0xbe9920fe,0x3f5233c6,0xbf121eb0,0x3f1ce11f,0xbf4a4c87,0x3f3263ef,0xbfeff573,0x3d55880e,0xbf7fa6e3,0xbe7ee6e1,0xbf77f110,0xbf06f686,0xbf5988ad,
0x3f800000,0x0,0x3f73530e,0xbe9f1cdf,0x3f4e8d90,0xbf173c07,0x3f1553b7,0xbf4fefa8,0x3f1aa086,0xbff40bdd,0xbc16cb58,0xbf7ffd39,0xbea395c5,0xbf7294f8,0xbf19210f,0xbf4d26fd,
0x3f800000,0x0,0x3f725470,0xbea5129f,0x3f4ac77f,0xbf1c420c,0x3f0d9281,0xbf554aa4,0x3f027dc0,0xbff78bc5,0xbd9064b4,0xbf7f5ce9,0xbec6d529,0xbf6be858,0xbf2a2a80,0xbf3f41fc,
0x3f800000,0x0,0x3f714c7a,0xbeab0201,0x3f46e22a,0xbf212ff9,0x3f05a02c,0xbf5a5ba0,0x3ed41501,0xbffa7302,0xbe06b26e,0xbf7dc68c,0xbee900b7,0xbf63f473,0xbf39f2ac,0xbf2ff3e6,
0x3f800000,0x0,0x3f703b37,0xbeb0eacb,0x3f42de29,0xbf26050a,0x3efafef7,0xbf5f20db,0x3ea2abb6,0xbffcbfc9,0xbe44b0b9,0xbf7b3bab,0xbf04f484,0xbf5ac450,0xbf485bca,0xbf1f599f,
0x3f800000,0x0,0x3f6f20b0,0xbeb6ccc3,0x3f3ebc1b,0xbf2ac082,0x3eea6681,0xbf6398ac,0x3e61bc2e,0xbffe70b0,0xbe80f8c0,0xbf77beb7,0xbf14b039,0xbf5064af,0xbf554aa4,0xbf0d9281,
0x3f800000,0x0,0x3f6dfcf2,0xbebca7af,0x3f3a7ca4,0xbf2f61a5,0x3ed97cb9,0xbf67c187,0x3dfb2b74,0xbfff84ab,0xbe9f1cdf,0xbf73530e,0xbf239da9,0xbf44e3f5,0xbf60a6cf,0xbef58035,
0x3f800000,0x0,0x3f6cd007,0xbec27b55,0x3f36206c,0xbf33e7bc,0x3ec8477c,0xbf6b99fb,0x3cc90e90,0xbffffb11,0xbebca7af,0xbf6dfcf2,0xbf31a81d,0xbf385216,0xbf6a5ad9,0xbece0bea,
0x3f800000,0x0,0x0,0x0,0x0,0x0,0x0,0x0,0x0,0x0,0x0,0x0,0x0,0x0,0x0,0x0,
0x0,0x0,0x0,0x0,0x0,0x0,0x0,0x0,0x0,0x0,0x0,0x0,0x0,0x0,0x0,0x0,
0x0,0x0,0x3e000000,0xbf20dff7,0x3ed0c429,0x0,0x3e000000,0x3e61f78b,0x3e0a8bd4,0x0,0x3e000000,0x3d5413cd,0x3d5df9ad,0x0,0x3e000000,0x3cf043ab,
0x0,0x0,0x3e000000,0x3ccbafaf,0xbd5df9ad,0x0,0x3e000000,0x3cf043ab,0xbe0a8bd4,0x0,0x3e000000,0x3d5413cd,0xbed0c429,0x0,0x3e000000,0x3e61f78b,
0x0,0x0,0x0,0x0,0x3f000000,0x0,0x0,0x3f000000,0x0,0x0,0x0,0x0,0x0,0x0,0x0,0x0,
0x0,0x0,0x0,0x0,0x0,0x0,0x0,0x0,0x0,0x0,0x0,0x0,0x3f000000,0x0,0x0,0xbf000000,
0x0,0x0,0x3e000000,0xbe3f90c7,0xbe8b7e3f,0x0,0x3e000000,0xbeb641af,0x3ea73d75,0x0,0x3e000000,0x3e9a827a,0x3da61ad1,0x0,0x3e000000,0x3dd906bd,
0x0,0x0,0x3e000000,0x3dab0dc1,0xbda61ad1,0x0,0x3e000000,0x3dd906bd,0xbea73d75,0x0,0x3e000000,0x3e9a827a,0x3e8b7e3f,0x0,0x3e000000,0xbeb641af,
0x0,0x0,0x0,0x0,0x0,0x0,0x0,0x0,0x3f000000,0x0,0x0,0x3f000000,0x0,0x0,0x0,0x0,
0x0,0x0,0x0,0x0,0x0,0x0,0x0,0x0,0x3f000000,0x0,0x0,0xbf000000,0x0,0x0,0x0,0x0,
0x0,0x0,0x3e000000,0xbdab0dc1,0xbda61ad1,0x0,0x3e000000,0xbdd906bd,0xbea73d75,0x0,0x3e000000,0xbe9a827a,0x3e8b7e3f,0x0,0x3e000000,0x3eb641af,
0x0,0x0,0x3e000000,0x3e3f90c7,0xbe8b7e3f,0x0,0x3e000000,0x3eb641af,0x3ea73d75,0x0,0x3e000000,0xbe9a827a,0x3da61ad1,0x0,0x3e000000,0xbdd906bd,
0x0,0x0,0x0,0x0,0x0,0x0,0x0,0x0,0x0,0x0,0x0,0x0,0x3f000000,0x0,0x0,0x3f000000,
0x0,0x0,0x0,0x0,0x3f000000,0x0,0x0,0xbf000000,0x0,0x0,0x0,0x0,0x0,0x0,0x0,0x0,
0x0,0x0,0x3e000000,0xbccbafaf,0xbd5df9ad,0x0,0x3e000000,0xbcf043ab,0xbe0a8bd4,0x0,0x3e000000,0xbd5413cd,0xbed0c429,0x0,0x3e000000,0xbe61f78b,
0x0,0x0,0x3e000000,0x3f20dff7,0x3ed0c429,0x0,0x3e000000,0xbe61f78b,0x3e0a8bd4,0x0,0x3e000000,0xbd5413cd,0x3d5df9ad,0x0,0x3e000000,0xbcf043ab,
};

struct Params {
    const __nv_bfloat16 *wr, *wi, *lre, *lim, *ldt, *dsk;
    float* out;
};

struct cf { float x, y; };
#define YIELD() asm volatile("pmevent 1;")
#define YS 15
#define YIELD_S1() do { if (YS & 1) YIELD(); } while (0)
#define YIELD_S2() do { if (YS & 2) YIELD(); } while (0)
#define YIELD_S3() do { if (YS & 4) YIELD(); } while (0)
__device__ __forceinline__ uint32_t smem_u32(const void* p) { return (uint32_t)__cvta_generic_to_shared(p); }
__device__ __forceinline__ void mbar_init(uint32_t a, uint32_t c) { asm volatile("mbarrier.init.shared::cta.b64 [%0], %1;" ::"r"(a), "r"(c) : "memory"); }
__device__ __forceinline__ void mbar_expect_tx(uint32_t a, uint32_t b) { asm volatile("mbarrier.arrive.expect_tx.shared::cta.b64 _, [%0], %1;" ::"r"(a), "r"(b) : "memory"); }
__device__ __forceinline__ void mbar_arrive(uint32_t a) { asm volatile("mbarrier.arrive.shared::cta.b64 _, [%0];" ::"r"(a) : "memory"); }
__device__ __forceinline__ void warp_arrive(uint32_t a) {
    __syncwarp();
    asm volatile("{.reg .pred p; elect.sync _|p, 0xffffffff; @p mbarrier.arrive.shared::cta.b64 _, [%0];}" ::"r"(a) : "memory");
}
__device__ __forceinline__ uint32_t mbar_try(uint32_t a, uint32_t ph) {
    uint32_t ok;
    asm volatile("{.reg .pred p; mbarrier.try_wait.parity.shared::cta.b64 p, [%1], %2; selp.u32 %0, 1, 0, p;}" : "=r"(ok) : "r"(a), "r"(ph) : "memory");
    return ok;
}
__device__ __forceinline__ void mbar_wait(uint32_t a, uint32_t ph) {
    uint32_t ok, n = 0;
    do { ok = mbar_try(a, ph); } while (!ok && ++n < SPIN_LIMIT);
}
__device__ __forceinline__ void mbar_wait_fast(uint32_t a, uint32_t ph) { if (!mbar_try(a, ph)) mbar_wait(a, ph); }
__device__ __forceinline__ unsigned ld_rlx(const unsigned* p) { unsigned v; asm volatile("ld.relaxed.gpu.global.u32 %0, [%1];" : "=r"(v) : "l"(p) : "memory"); return v; }
__device__ __forceinline__ void wait_cnt(const unsigned* p, unsigned target) {
    unsigned n = 0;
    while ((int)(ld_rlx(p) - target) < 0 && ++n < SPIN_LIMIT) __nanosleep(20);
}
__device__ __forceinline__ void red_hint(unsigned* p) { asm volatile("red.relaxed.gpu.global.add.u32 [%0], 1;" ::"l"(p) : "memory"); }
__device__ __forceinline__ void fence_async() { asm volatile("fence.proxy.async.global;" ::: "memory"); }
__device__ __forceinline__ void fence_async_sm() { asm volatile("fence.proxy.async.shared::cta;" ::: "memory"); }
#define bar_sync(id, n) asm volatile("bar.sync %0, %1;" ::"n"(id), "n"(n) : "memory")
#define bar_arrive(id, n) asm volatile("bar.arrive %0, %1;" ::"n"(id), "n"(n) : "memory")
__device__ __forceinline__ bool elect_one() {
    uint32_t r;
    asm volatile("{.reg .pred p; elect.sync _|p, 0xffffffff; selp.u32 %0, 1, 0, p;}" : "=r"(r));
    return r != 0;
}

__device__ __forceinline__ void tma2d(uint32_t dst, const CUtensorMap* m, int c0, int c1, uint32_t bar) {
    asm volatile("cp.async.bulk.tensor.2d.shared::cluster.global.mbarrier::complete_tx::bytes [%0], [%1, {%3,%4}], [%2];" ::"r"(dst), "l"(m), "r"(bar), "r"(c0), "r"(c1) : "memory");
}
__device__ __forceinline__ void tma3d(uint32_t dst, const CUtensorMap* m, int c0, int c1, int c2, uint32_t bar) {
    asm volatile("cp.async.bulk.tensor.3d.shared::cluster.global.mbarrier::complete_tx::bytes [%0], [%1, {%3,%4,%5}], [%2];" ::"r"(dst), "l"(m), "r"(bar), "r"(c0), "r"(c1), "r"(c2) : "memory");
}
__device__ __forceinline__ void tma2d_mc(uint32_t dst, const CUtensorMap* m, int c0, int c1, uint32_t bar) {
    asm volatile("cp.async.bulk.tensor.2d.shared::cluster.global.mbarrier::complete_tx::bytes.multicast::cluster [%0], [%1, {%3,%4}], [%2], %5;" ::"r"(dst), "l"(m), "r"(bar), "r"(c0), "r"(c1), "h"((uint16_t)3) : "memory");
}
__device__ __forceinline__ void tma4d_mc(uint32_t dst, const CUtensorMap* m, int c0, int c1, int c2, int c3, uint32_t bar) {
    asm volatile("cp.async.bulk.tensor.4d.shared::cluster.global.mbarrier::complete_tx::bytes.multicast::cluster [%0], [%1, {%3,%4,%5,%6}], [%2], %7;" ::"r"(dst), "l"(m), "r"(bar), "r"(c0), "r"(c1), "r"(c2), "r"(c3), "h"((uint16_t)3) : "memory");
}
__device__ __forceinline__ void tma4d(uint32_t dst, const CUtensorMap* m, int c0, int c1, int c2, int c3, uint32_t bar) {
    asm volatile("cp.async.bulk.tensor.4d.shared::cluster.global.mbarrier::complete_tx::bytes [%0], [%1, {%3,%4,%5,%6}], [%2];" ::"r"(dst), "l"(m), "r"(bar), "r"(c0), "r"(c1), "r"(c2), "r"(c3) : "memory");
}
__device__ __forceinline__ void tma2d_st(const CUtensorMap* m, int c0, int c1, uint32_t src) {
    asm volatile("cp.async.bulk.tensor.2d.global.shared::cta.bulk_group [%0, {%2,%3}], [%1];" ::"l"(m), "r"(src), "r"(c0), "r"(c1) : "memory");
}
__device__ __forceinline__ void tma3d_st(const CUtensorMap* m, int c0, int c1, int c2, uint32_t src) {
    asm volatile("cp.async.bulk.tensor.3d.global.shared::cta.bulk_group [%0, {%2,%3,%4}], [%1];" ::"l"(m), "r"(src), "r"(c0), "r"(c1), "r"(c2) : "memory");
}
__device__ __forceinline__ void tma5d(uint32_t dst, const CUtensorMap* m, int c0, int c1, int c2, int c3, int c4, uint32_t bar) {
    asm volatile("cp.async.bulk.tensor.5d.shared::cluster.global.mbarrier::complete_tx::bytes [%0], [%1, {%3,%4,%5,%6,%7}], [%2];" ::"r"(dst), "l"(m), "r"(bar), "r"(c0), "r"(c1), "r"(c2), "r"(c3), "r"(c4) : "memory");
}
__device__ __forceinline__ void tma5d_mc(uint32_t dst, const CUtensorMap* m, int c0, int c1, int c2, int c3, int c4, uint32_t bar) {
    asm volatile("cp.async.bulk.tensor.5d.shared::cluster.global.mbarrier::complete_tx::bytes.multicast::cluster [%0], [%1, {%3,%4,%5,%6,%7}], [%2], %8;" ::"r"(dst), "l"(m), "r"(bar), "r"(c0), "r"(c1), "r"(c2), "r"(c3), "r"(c4), "h"((uint16_t)3) : "memory");
}
__device__ __forceinline__ void bulk_pf(const void* src, uint32_t n) { asm volatile("cp.async.bulk.prefetch.L2.global [%0], %1;" ::"l"(src), "r"(n) : "memory"); }
__device__ __forceinline__ void tma4d_pf(const CUtensorMap* m, int c0, int c1, int c2, int c3) {
    asm volatile("cp.async.bulk.prefetch.tensor.4d.L2.global [%0, {%1,%2,%3,%4}];" ::"l"(m), "r"(c0), "r"(c1), "r"(c2), "r"(c3) : "memory");
}
__device__ __forceinline__ void tma5d_pf(const CUtensorMap* m, int c0, int c1, int c2, int c3, int c4) {
    asm volatile("cp.async.bulk.prefetch.tensor.5d.L2.global [%0, {%1,%2,%3,%4,%5}];" ::"l"(m), "r"(c0), "r"(c1), "r"(c2), "r"(c3), "r"(c4) : "memory");
}
__device__ __forceinline__ void bulk_ld(uint32_t dst, const void* src, uint32_t n, uint32_t bar) {
    asm volatile("cp.async.bulk.shared::cluster.global.mbarrier::complete_tx::bytes [%0], [%1], %2, [%3];" ::"r"(dst), "l"(src), "r"(n), "r"(bar) : "memory");
}
__device__ __forceinline__ void bulk_st(void* dst, uint32_t src, uint32_t n) {
    asm volatile("cp.async.bulk.global.shared::cta.bulk_group [%0], [%1], %2;" ::"l"(dst), "r"(src), "r"(n) : "memory");
}
__device__ __forceinline__ void bulk_commit() { asm volatile("cp.async.bulk.commit_group;" ::: "memory"); }
__device__ __forceinline__ void bulk_wait_read() { asm volatile("cp.async.bulk.wait_group.read 0;" ::: "memory"); }
__device__ __forceinline__ void bulk_wait_all() { asm volatile("cp.async.bulk.wait_group 0;" ::: "memory"); }
__device__ __forceinline__ void stsm4(uint32_t a, uint32_t r0, uint32_t r1, uint32_t r2, uint32_t r3) {
    asm volatile("stmatrix.sync.aligned.m8n8.x4.shared.b16 [%0], {%1,%2,%3,%4};" ::"r"(a), "r"(r0), "r"(r1), "r"(r2), "r"(r3) : "memory");
}
__device__ __forceinline__ void sts128(uint32_t a, uint32_t r0, uint32_t r1, uint32_t r2, uint32_t r3) {
    asm volatile("st.shared.v4.b32 [%0], {%1,%2,%3,%4};" ::"r"(a), "r"(r0), "r"(r1), "r"(r2), "r"(r3) : "memory");
}
__device__ __forceinline__ void lds128f(uint32_t a, float& x, float& y, float& z, float& u) { asm volatile("ld.shared.v4.f32 {%0,%1,%2,%3}, [%4];" : "=f"(x), "=f"(y), "=f"(z), "=f"(u) : "r"(a) : "memory"); }
__device__ __forceinline__ cf lds_cf(uint32_t a) { cf v; asm volatile("ld.shared.v2.f32 {%0,%1}, [%2];" : "=f"(v.x), "=f"(v.y) : "r"(a) : "memory"); return v; }
__device__ __forceinline__ void stg128(const void* a, uint32_t r0, uint32_t r1, uint32_t r2, uint32_t r3) {
    asm volatile("st.global.v4.b32 [%0], {%1,%2,%3,%4};" ::"l"(a), "r"(r0), "r"(r1), "r"(r2), "r"(r3) : "memory");
}
__device__ __forceinline__ int fresh_lane() { int v; asm volatile("mov.u32 %0, %%laneid;" : "=r"(v)); return v; }
__device__ __forceinline__ uint32_t opaque32(uint32_t v) { asm volatile("" : "+r"(v)); return v; }
__device__ __forceinline__ const uint8_t* padd(const void* base, uint32_t off) {
    uint64_t r;
    asm("{.reg .u32 l, h; mov.b64 {l, h}, %1; add.cc.u32 l, l, %2; addc.u32 h, h, 0; mov.b64 %0, {l, h};}" : "=l"(r) : "l"(base), "r"(off));
    return (const uint8_t*)r;
}
template <int N, int STRIDE> __device__ __forceinline__ void ldtab(uint32_t (&v)[4 * N], uint32_t off) {
    const uint8_t* a = padd(g_tab, off);
#pragma unroll
    for (int i = 0; i < N; i++)
        asm volatile("ld.global.nc.v4.b32 {%0,%1,%2,%3}, [%4];" : "=r"(v[4 * i]), "=r"(v[4 * i + 1]), "=r"(v[4 * i + 2]), "=r"(v[4 * i + 3]) : "l"(a + i * STRIDE));
}
template <int STRIDE> __device__ __forceinline__ void ldtab_cf(cf (&t)[8], uint32_t off) {
    uint32_t v[16];
    ldtab<4, STRIDE>(v, off);
#pragma unroll
    for (int i = 0; i < 8; i++) t[i] = {__uint_as_float(v[2 * i]), __uint_as_float(v[2 * i + 1])};
}
__device__ __forceinline__ uint32_t lds16(uint32_t a) { uint32_t v; asm volatile("ld.shared.u16 %0, [%1];" : "=r"(v) : "r"(a)); return v; }
__device__ __forceinline__ unsigned get_epoch(uint32_t bars) {
    mbar_wait(bars + B_EP, 0);
    unsigned e;
    asm volatile("ld.shared.u32 %0, [%1];" : "=r"(e) : "r"(bars + B_EPOCH) : "memory");
    return e;
}
__device__ __forceinline__ void sts64(uint32_t a, uint32_t x, uint32_t y) { asm volatile("st.shared.v2.b32 [%0], {%1,%2};" ::"r"(a), "r"(x), "r"(y) : "memory"); }
__device__ __forceinline__ uint32_t pk(float lo, float hi) { uint32_t r; asm("cvt.rn.bf16x2.f32 %0, %1, %2;" : "=r"(r) : "f"(hi), "f"(lo)); return r; }
__device__ __forceinline__ float bf2f(unsigned short v) { return __uint_as_float((uint32_t)v << 16); }

__device__ __forceinline__ uint64_t mkdesc(uint32_t addr, uint32_t lbo, uint32_t sbo, uint32_t swz) {
    return (uint64_t)((addr & 0x3FFFF) >> 4) | ((uint64_t)(lbo >> 4) << 16) | ((uint64_t)(sbo >> 4) << 32) | ((uint64_t)swz << 62);
}
__device__ __forceinline__ uint64_t opaque(uint64_t v) { asm volatile("" : "+l"(v)); return v; }
__device__ __forceinline__ void wg_fence() { asm volatile("wgmma.fence.sync.aligned;" ::: "memory"); }
__device__ __forceinline__ void wg_commit() { asm volatile("wgmma.commit_group.sync.aligned;" ::: "memory"); }
template <int N> __device__ __forceinline__ void wg_wait() { asm volatile("wgmma.wait_group.sync.aligned %0;" ::"n"(N) : "memory"); }
template <int N> __device__ __forceinline__ void pin(float (&d)[N]) {
#pragma unroll
    for (int i = 0; i < N; i++) asm volatile("" : "+f"(d[i])::"memory");
}
template <int N> __device__ __forceinline__ void pinu(uint32_t (&d)[N]) {
#pragma unroll
    for (int i = 0; i < N; i++) asm volatile("" : "+r"(d[i])::"memory");
}

#define R8(d, o) "+f"(d[o]), "+f"(d[o + 1]), "+f"(d[o + 2]), "+f"(d[o + 3]), "+f"(d[o + 4]), "+f"(d[o + 5]), "+f"(d[o + 6]), "+f"(d[o + 7])
#define L8 "%0,%1,%2,%3,%4,%5,%6,%7"
#define L32 L8 ",%8,%9,%10,%11,%12,%13,%14,%15,%16,%17,%18,%19,%20,%21,%22,%23,%24,%25,%26,%27,%28,%29,%30,%31"
#define L56 L32 ",%32,%33,%34,%35,%36,%37,%38,%39,%40,%41,%42,%43,%44,%45,%46,%47,%48,%49,%50,%51,%52,%53,%54,%55"
#define L64 L56 ",%56,%57,%58,%59,%60,%61,%62,%63"

template <int O, int TA, int TB, int N> __device__ __forceinline__ void mma128_ss(float (&d)[N], uint64_t da, uint64_t db, int sc) {
    asm volatile("{.reg .pred p; setp.ne.b32 p, %66, 0;\n"
                 "wgmma.mma_async.sync.aligned.m64n128k16.f32.bf16.bf16 {" L64 "}, %64, %65, p, 1, 1, %67, %68;}"
                 : R8(d, O), R8(d, O + 8), R8(d, O + 16), R8(d, O + 24), R8(d, O + 32), R8(d, O + 40), R8(d, O + 48), R8(d, O + 56)
                 : "l"(da), "l"(db), "r"(sc), "n"(TA), "n"(TB));
}
template <int O, int TB> __device__ __forceinline__ void mma128_rs(float (&d)[128], uint32_t a0, uint32_t a1, uint32_t a2, uint32_t a3, uint64_t db, int sc) {
    asm volatile("{.reg .pred p; setp.ne.b32 p, %69, 0;\n"
                 "wgmma.mma_async.sync.aligned.m64n128k16.f32.bf16.bf16 {" L64 "}, {%64,%65,%66,%67}, %68, p, 1, 1, %70;}"
                 : R8(d, O), R8(d, O + 8), R8(d, O + 16), R8(d, O + 24), R8(d, O + 32), R8(d, O + 40), R8(d, O + 48), R8(d, O + 56)
                 : "r"(a0), "r"(a1), "r"(a2), "r"(a3), "l"(db), "r"(sc), "n"(TB));
}
template <int TB> __device__ __forceinline__ void mma64_rs(float (&d)[32], uint32_t a0, uint32_t a1, uint32_t a2, uint32_t a3, uint64_t db, int sc) {
    asm volatile("{.reg .pred p; setp.ne.b32 p, %37, 0;\n"
                 "wgmma.mma_async.sync.aligned.m64n64k16.f32.bf16.bf16 {" L32 "}, {%32,%33,%34,%35}, %36, p, 1, 1, %38;}"
                 : R8(d, 0), R8(d, 8), R8(d, 16), R8(d, 24)
                 : "r"(a0), "r"(a1), "r"(a2), "r"(a3), "l"(db), "r"(sc), "n"(TB));
}
__device__ __forceinline__ void mma112_ss(float (&d)[64], uint64_t da, uint64_t db, int sc) {
    asm volatile("{.reg .pred p; setp.ne.b32 p, %58, 0;\n"
                 "wgmma.mma_async.sync.aligned.m64n112k16.f32.bf16.bf16 {" L56 "}, %56, %57, p, 1, 1, 0, 1;}"
                 : R8(d, 8), R8(d, 16), R8(d, 24), R8(d, 32), R8(d, 40), R8(d, 48), R8(d, 56)
                 : "l"(da), "l"(db), "r"(sc));
}
__device__ __forceinline__ void mma16_rs(float (&d)[64], uint32_t a0, uint32_t a1, uint32_t a2, uint32_t a3, uint64_t db, int sc) {
    asm volatile("{.reg .pred p; setp.ne.b32 p, %13, 0;\n"
                 "wgmma.mma_async.sync.aligned.m64n16k16.f32.bf16.bf16 {" L8 "}, {%8,%9,%10,%11}, %12, p, 1, 1, 1;}"
                 : R8(d, 0)
                 : "r"(a0), "r"(a1), "r"(a2), "r"(a3), "l"(db), "r"(sc));
}

__device__ __forceinline__ cf cmul(cf a, cf b) { return {fmaf(a.x, b.x, -a.y * b.y), fmaf(a.x, b.y, a.y * b.x)}; }
__device__ __forceinline__ cf cmulc(cf a, cf b) { return {fmaf(a.x, b.x, a.y * b.y), fmaf(a.y, b.x, -a.x * b.y)}; }
__device__ __forceinline__ cf cfma(cf a, cf b, cf c) { return {fmaf(a.x, b.x, fmaf(-a.y, b.y, c.x)), fmaf(a.x, b.y, fmaf(a.y, b.x, c.y))}; }
__device__ __forceinline__ cf csq(cf a) { return {fmaf(a.x, a.x, -a.y * a.y), (a.x * a.y) * 2.f}; }
__device__ __forceinline__ cf csel(int c, cf a, cf b) {
    cf r;
    asm("{.reg .pred p; setp.ne.s32 p, %2, 0; selp.f32 %0, %3, %5, p; selp.f32 %1, %4, %6, p;}" : "=f"(r.x), "=f"(r.y) : "r"(c), "f"(a.x), "f"(a.y), "f"(b.x), "f"(b.y));
    return r;
}
__device__ __forceinline__ cf cadd(cf a, cf b) { return {a.x + b.x, a.y + b.y}; }
__device__ __forceinline__ cf csub(cf a, cf b) { return {a.x - b.x, a.y - b.y}; }
__device__ __forceinline__ cf twice_minus(cf a, cf s) { return {fmaf(2.f, a.x, -s.x), fmaf(2.f, a.y, -s.y)}; }
__device__ __forceinline__ cf twid(int m, int M) {
    int r = ((m + M / 2) & (M - 1)) - M / 2;
    float s, c;
    __sincosf((float)r * (-6.283185307179586f / (float)M), &s, &c);
    return {c, s};
}
struct c2 { cf a, b; };
#define YP1 3
#define YP2 0
#define YP3 0
template <int Y> __device__ __forceinline__ void fin(c2& u) { if (Y & 1) asm volatile("pmevent 1;" : "+f"(u.a.x), "+f"(u.a.y), "+f"(u.b.x), "+f"(u.b.y)); }
template <int Y> __device__ __forceinline__ void fin(c2& u, c2& v) {
    if (Y & 2) asm volatile("pmevent 1;" : "+f"(u.a.x), "+f"(u.a.y), "+f"(u.b.x), "+f"(u.b.y), "+f"(v.a.x), "+f"(v.a.y), "+f"(v.b.x), "+f"(v.b.y));
}
__device__ __forceinline__ c2 mul2(c2 u, cf t) { return {cmul(u.a, t), cmul(u.b, t)}; }
__device__ __forceinline__ c2 mul2(c2 u, c2 t) { return {cmul(u.a, t.a), cmul(u.b, t.b)}; }
__device__ __forceinline__ c2 fma2(c2 u, cf t, c2 c) { return {cfma(u.a, t, c.a), cfma(u.b, t, c.b)}; }
__device__ __forceinline__ c2 fma2(c2 u, c2 t, c2 c) { return {cfma(u.a, t.a, c.a), cfma(u.b, t.b, c.b)}; }
__device__ __forceinline__ c2 twm2(c2 u, c2 s) { return {twice_minus(u.a, s.a), twice_minus(u.b, s.b)}; }
template <int Y> __device__ __forceinline__ void bfly(c2& u, c2& v) { const c2 t = u; u = {cadd(t.a, v.a), cadd(t.b, v.b)}; v = {csub(t.a, v.a), csub(t.b, v.b)}; fin<Y>(u, v); }
template <int Y> __device__ __forceinline__ void bfly_mi(c2& u, c2& v) {
    const c2 t = u, z = v;
    u = {{t.a.x + z.a.y, t.a.y - z.a.x}, {t.b.x + z.b.y, t.b.y - z.b.x}};
    v = {{t.a.x - z.a.y, t.a.y + z.a.x}, {t.b.x - z.b.y, t.b.y + z.b.x}};
    fin<Y>(u, v);
}
template <int Y> __device__ __forceinline__ void bfly_s(c2& u, c2& v) {
    const float s = 0.70710678118654752f;
    const c2 t = u, z = v;
    u = {{fmaf(s, z.a.x, t.a.x), fmaf(s, z.a.y, t.a.y)}, {fmaf(s, z.b.x, t.b.x), fmaf(s, z.b.y, t.b.y)}};
    v = {{fmaf(-s, z.a.x, t.a.x), fmaf(-s, z.a.y, t.a.y)}, {fmaf(-s, z.b.x, t.b.x), fmaf(-s, z.b.y, t.b.y)}};
    fin<Y>(u, v);
}
template <int Y, class T> __device__ __forceinline__ void bfly_tw(c2& u0, c2& v0, T t0, c2& u1, c2& v1, T t1) {
    v0 = fma2(v0, t0, u0); fin<Y>(v0);
    v1 = fma2(v1, t1, u1); fin<Y>(v1);
    const c2 a = twm2(u0, v0), b = twm2(u1, v1);
    u0 = v0; u1 = v1; v0 = a; v1 = b;
    fin<Y>(v0, v1);
}
template <bool TW, int Y> __device__ __forceinline__ void dft8(c2 (&v)[8], const cf (&tw)[8]) {
    if (TW) {
#pragma unroll
        for (int n = 1; n < 4; n++) { v[n] = mul2(v[n], tw[n]); fin<Y>(v[n]); }
        bfly_tw<Y>(v[0], v[4], tw[4], v[2], v[6], tw[6]);
        bfly_tw<Y>(v[1], v[5], tw[5], v[3], v[7], tw[7]);
    } else {
#pragma unroll
        for (int n = 0; n < 4; n++) bfly<Y>(v[n], v[n + 4]);
    }
    bfly<Y>(v[0], v[2]); bfly_mi<Y>(v[4], v[6]);
    bfly<Y>(v[1], v[3]); bfly_mi<Y>(v[5], v[7]);
    v[5] = {{v[5].a.x + v[5].a.y, v[5].a.y - v[5].a.x}, {v[5].b.x + v[5].b.y, v[5].b.y - v[5].b.x}};
    v[7] = {{v[7].a.y - v[7].a.x, -v[7].a.x - v[7].a.y}, {v[7].b.y - v[7].b.x, -v[7].b.x - v[7].b.y}};
    fin<Y>(v[5], v[7]);
    bfly<Y>(v[0], v[1]); bfly_s<Y>(v[4], v[5]); bfly_mi<Y>(v[2], v[3]); bfly_s<Y>(v[6], v[7]);
    const c2 t1 = v[1], t3 = v[3];
    v[1] = v[4]; v[4] = t1; v[3] = v[6]; v[6] = t3;
}

__device__ __forceinline__ void gather(uint64_t (&fv)[4], const uint8_t* a, int n) {
    asm volatile("{.reg .pred p0, p1, p2, p3;\n"
                 "setp.ge.s32 p0, %5, 0; setp.ge.s32 p1, %5, 4; setp.ge.s32 p2, %5, 8; setp.ge.s32 p3, %5, 12;\n"
                 "@p0 ld.relaxed.gpu.global.b64 %0, [%4]; @p1 ld.relaxed.gpu.global.b64 %1, [%4+-32768];\n"
                 "@p2 ld.relaxed.gpu.global.b64 %2, [%4+-65536]; @p3 ld.relaxed.gpu.global.b64 %3, [%4+-98304];}"
                 : "+l"(fv[0]), "+l"(fv[1]), "+l"(fv[2]), "+l"(fv[3]) : "l"(a), "r"(n) : "memory");
}
__device__ __forceinline__ cf as_cf(uint64_t v) { cf r; asm("mov.b64 {%0,%1}, %2;" : "=f"(r.x), "=f"(r.y) : "l"(v)); return r; }
template <int H> __device__ __forceinline__ void prescale(float (&u)[64], const float (&d)[128], cf gam) {
#pragma unroll
    for (int i = 0; i < 32; i += 2) {
        const int r = 2 * i + 2 * H;
        c2 v = mul2(c2{{d[r], -d[64 + r]}, {d[r + 1], -d[65 + r]}}, gam);
        if (YS & 2) asm volatile("pmevent 1;" : "+f"(v.a.x), "+f"(v.a.y), "+f"(v.b.x), "+f"(v.b.y));
        u[i] = v.a.x; u[32 + i] = v.a.y; u[i + 1] = v.b.x; u[33 + i] = v.b.y;
    }
}
__device__ __forceinline__ void scan2(const float (&u)[64], cf lam, cf st, const uint8_t* hptr, uint32_t hm, uint32_t hb, uint32_t& keep) {
    uint32_t hp[32];
#pragma unroll
    for (int jj = 0; jj < 4; jj++) {
        cf v[8];
#pragma unroll
        for (int i = 0; i < 8; i++) v[i] = st = cfma(lam, st, {u[8 * jj + i], u[32 + 8 * jj + i]});
        const int o = 8 * jj;
        hp[o] = pk(v[0].x, v[2].x); hp[o + 1] = pk(v[4].x, v[6].x); hp[o + 2] = pk(v[1].x, v[3].x); hp[o + 3] = pk(v[5].x, v[7].x);
        hp[o + 4] = pk(v[0].y, v[2].y); hp[o + 5] = pk(v[4].y, v[6].y); hp[o + 6] = pk(v[1].y, v[3].y); hp[o + 7] = pk(v[5].y, v[7].y);
        hp[o + jj] = (hp[o + jj] & hm) | hb;
        hp[o + 4 + jj] = (hp[o + 4 + jj] & hm) | hb;
        stg128(hptr + (jj >> 1) * 8192 + (jj & 1) * 512, hp[o], hp[o + 1], hp[o + 2], hp[o + 3]);
        stg128(hptr + 16384 + (jj >> 1) * 8192 + (jj & 1) * 512, hp[o + 4], hp[o + 5], hp[o + 6], hp[o + 7]);
        YIELD_S3();
        if (jj > 0) {
#pragma unroll
            for (int i = o - 8; i < o; i += 2) asm volatile("lop3.b32 %0, %0, %1, %2, 0x80;" : "+r"(keep) : "r"(hp[i]), "r"(hp[i + 1]));
        }
    }
}

__device__ __forceinline__ int pos_of(int n) { return (n & 24) + 4 * (n & 1) + ((n >> 1) & 3); }
__device__ __forceinline__ int unit_of(int role, int u, int& slot) {
    const int g = role & 7, w = (role >> 3) & 3, b = role >> 5;
    slot = role >= 128 ? g : (g ? 16 * g + w + 4 * b : 4 * w + b);
    return role >= 128 ? 32 * max(2 * g + u, 1) : (g ? g + 16 * w : ((w & 1) << 4) + ((w & 2) << 2)) + 64 * b + 256 * u;
}
template <int STRIDE> __device__ __forceinline__ bool tags_ok(uint32_t a, uint32_t ep) {
    uint32_t v[4], ok;
#pragma unroll
    for (int i = 0; i < 4; i++) {
        if (STRIDE || !i) asm volatile("ld.shared.u32 %0, [%1];" : "=r"(v[i]) : "r"(a + i * STRIDE) : "memory");
        else v[i] = v[0];
    }
    asm volatile("{.reg .pred p; .reg .b32 a, b; lop3.b32 a, %1, %2, %5, 0x7e; lop3.b32 b, %3, %4, %5, 0x7e; lop3.b32 a, a, b, 1, 0xa8;\n"
                 "setp.eq.u32 p, a, 0; vote.sync.all.pred p, p, -1; selp.u32 %0, 1, 0, p;}" : "=r"(ok) : "r"(v[0]), "r"(v[1]), "r"(v[2]), "r"(v[3]), "r"(ep));
    return ok;
}
__device__ __forceinline__ void load_w_rows(uint32_t dst, const CUtensorMap* mr, const CUtensorMap* mi, int kap, uint32_t bar) {
    mbar_expect_tx(bar, 16 * WPITCH);
#pragma unroll 1
    for (int i = 0; i < 2; i++, dst += 8 * WPITCH, kap = (512 - kap) & 511) {
        tma2d(dst, mr, (kap * 1026 >> 4) * 2, 0, bar);
        tma2d(dst + 4 * WPITCH, mi, (kap * 1026 >> 4) * 2, 0, bar);
    }
}
__device__ __forceinline__ void prefetch_w_rows(const CUtensorMap* mr, const CUtensorMap* mi, int kap) {
#pragma unroll 1
    for (int i = 0; i < 2; i++, kap = (512 - kap) & 511) {
        asm volatile("cp.async.bulk.prefetch.tensor.2d.L2.global [%0, {%1,%2}];" ::"l"(mr), "r"((kap * 1026 >> 4) * 2), "r"(0) : "memory");
        asm volatile("cp.async.bulk.prefetch.tensor.2d.L2.global [%0, {%1,%2}];" ::"l"(mi), "r"((kap * 1026 >> 4) * 2), "r"(0) : "memory");
    }
}
__device__ __forceinline__ void store_v(const uint32_t (&vo)[32], const uint8_t* vp, int k, bool p) {
    asm volatile("{.reg .pred p; setp.ne.u32 p, %3, 0; @p st.global.v2.b32 [%0], {%1,%2};}" ::"l"(vp + (k >> 2) * (1 << 20) + ((k >> 1) & 1) * 8192 + (k & 1) * (4 * 32768)), "r"(vo[2 * k]), "r"(vo[2 * k + 1]), "r"((int)p) : "memory");
}
__device__ __forceinline__ void hint_v(unsigned* cnt, int on) { asm volatile("{.reg .pred p; setp.ne.and.u32 p, %1, 0, p0; @p red.relaxed.gpu.global.add.u32 [%0], 1;}" ::"l"(cnt), "r"(on) : "memory"); }
#define SB0 1024
__device__ __forceinline__ uint64_t ring_desc(uint32_t sb, uint32_t off, uint32_t lbo, uint32_t swz) {
    uint64_t d;
    asm volatile("{.reg .b32 z; shr.u32 z, %1, 28; mov.b64 %0, {z, z}; add.u64 %0, %0, %2;}" : "=l"(d) : "r"(sb), "l"(mkdesc(SB0 + off, lbo, 1024, swz)));
    return d;
}
struct Ring {
    uint32_t full, rel;
    uint32_t n;
    bool sig;
};
__device__ __forceinline__ void ring_release(const Ring& r, uint32_t o) {
    if (r.sig) asm volatile("mbarrier.arrive.shared::cluster.b64 _, [%0];" ::"r"(r.rel + o) : "memory");
}
__device__ __forceinline__ void peek(uint32_t a, uint32_t ph) { asm volatile("mbarrier.test_wait.parity.shared::cta.b64 pk, [%0], %1;" ::"r"(a), "r"(ph) : "memory"); }
__device__ __forceinline__ void peek_wait(uint32_t a, uint32_t ph, uint32_t& n) {
    asm volatile("{@pk bra DONE;\n"
                 "LOOP: mbarrier.try_wait.parity.shared::cta.b64 pk, [%1], %2; add.u32 %0, %0, 1; setp.gt.or.u32 pk, %0, %3, pk; @!pk bra LOOP;\n"
                 "DONE: }" : "+r"(n) : "r"(a), "r"(ph), "n"(SPIN_LIMIT) : "memory");
}
#define SL(k) ((k) % NST)
#define PH(k) (((k) / NST) & 1)
#define HANDPOS 5
#define H64 "%64,%65,%66,%67,%68,%69,%70,%71,%72,%73,%74,%75,%76,%77,%78,%79,%80,%81,%82,%83,%84,%85,%86,%87,%88,%89,%90,%91,%92,%93,%94,%95," \
            "%96,%97,%98,%99,%100,%101,%102,%103,%104,%105,%106,%107,%108,%109,%110,%111,%112,%113,%114,%115,%116,%117,%118,%119,%120,%121,%122,%123,%124,%125,%126,%127"
#define WG_MMA "wgmma.mma_async.sync.aligned.m64n128k16.f32.bf16.bf16 "
#define DESC_B(S, j) "mov.b64 {t, hb}, %130; mov.b64 db, {%137 + 2048 * " #S " + 2 * " #j ", hb};\n"
#define MMA_LO(S, j, p) "add.u64 da, %129, 2048 * " #S " + %136 * " #j ";" DESC_B(S, j) WG_MMA "{" L64 "}, da, db, " #p ", 1, 1, %138, 0;\n"
#define MMA_HI(S, j, p) "add.u64 da, %129, 2048 * " #S " + 512 + %136 * " #j ";\n" WG_MMA "{" H64 "}, da, db, " #p ", 1, 1, %138, 0;\n"
#define STEP(S, P, N, ph, pa, pr, X, Y) \
    "wgmma.fence.sync.aligned;\n" MMA_LO(S, 0, pa) MMA_HI(S, 0, pa) \
    "wgmma.commit_group.sync.aligned; wgmma.wait_group.sync.aligned 1; @" #pr " mbarrier.arrive.shared::cluster.b64 _, [%132 + 8 * " #P "];\n" MMA_LO(S, 1, 1) \
    "mbarrier.test_wait.parity.shared::cta.b64 pk, [%131 + 8 * " #N "], " #ph ";\n" MMA_HI(S, 1, 1) MMA_LO(S, 2, 1) X MMA_HI(S, 2, 1) MMA_LO(S, 3, 1) MMA_HI(S, 3, 1) \
    "wgmma.commit_group.sync.aligned;\n" P4A Y "@pk bra GO" #S ";\n" \
    "WAIT" #S ": mbarrier.try_wait.parity.shared::cta.b64 pk, [%131 + 8 * " #N "], " #ph "; add.u32 %128, %128, 1; setp.gt.or.u32 pk, %128, %139, pk; @!pk bra WAIT" #S ";\n" \
    "GO" #S ":\n" P4B
#define P4A
#define P4B
#define P4I
#define P4O
#define STEP_ARGS(TA) \
    : R8(d, 0), R8(d, 8), R8(d, 16), R8(d, 24), R8(d, 32), R8(d, 40), R8(d, 48), R8(d, 56), \
      R8(d, 64), R8(d, 72), R8(d, 80), R8(d, 88), R8(d, 96), R8(d, 104), R8(d, 112), R8(d, 120), "+r"(r.n) \
    : "l"(ha), "l"(hb), "r"(r.full), "r"(r.rel), "r"((uint32_t)r.sig), "r"(wg), \
      "n"(SB0 / 16 + (TA ? 32 << 16 : 1 << 16)), "n"(TA ? 128 : 2), "n"(SB0 / 16 + 1024 + (1 << 16)), "n"(TA), "n"(SPIN_LIMIT) P4O \
    : "memory"
#define STEP_REGS "{.reg .b32 k, t, ph, hb; .reg .b64 da, db; .reg .pred ps, pl, pa, pr;\n" P4I "setp.ne.u32 ps, %133, 0;\n"
__device__ __forceinline__ void gemm1(float (&d)[128], Ring& r, uint64_t ha, uint64_t hb, int wg) {
    asm volatile(STEP_REGS "mul.lo.u32 k, %134, 15; mov.b32 ph, %134; setp.ne.u32 pl, k, 0; @pl bra ONE;\n"
                 "LOOP: setp.ne.u32 pa, k, 0; and.pred pr, pa, ps; setp.eq.u32 pl, k, 15;\n"
                 STEP(0, 4, 1, ph, pa, pr, "@pl bar.arrive 1, 256;\n", "@pl bra END;\n")
                 "ONE: setp.ne.u32 pa, k, 15; and.pred pr, pa, ps; setp.eq.u32 pl, k, 30;\n"
                 STEP(1, 0, 2, ph, pa, pr, "@pl bar.arrive 2, 256;\n", "@pl bra END;\n")
                 STEP(2, 1, 3, ph, 1, ps, "", "") STEP(3, 2, 4, ph, 1, ps, "", "") "xor.b32 ph, ph, 1; add.u32 k, k, 5;\n" STEP(4, 3, 0, ph, 1, ps, "", "")
                 "bra LOOP;\n"
                 "END:\n" P4B "}" STEP_ARGS(0));
}
__device__ __forceinline__ void gemm2(float (&d)[128], Ring& r, uint64_t ha, uint64_t hb, int wg) {
    asm volatile(STEP_REGS "mov.b32 k, 0; mov.b32 ph, 0;\n"
                 "LOOP: setp.ne.u32 pa, k, 0; and.pred pr, pa, ps; setp.eq.u32 pl, k, 5;\n"
                 STEP(2, 1, 3, ph, pa, pr, "", "") STEP(3, 2, 4, ph, 1, ps, "", "") "xor.b32 ph, ph, 1; add.u32 k, k, 1;\n" STEP(4, 3, 0, ph, 1, ps, "", "")
                 "@pl bra END;\n" STEP(0, 4, 1, ph, 1, ps, "", "") STEP(1, 0, 2, ph, 1, ps, "", "")
                 "bra LOOP;\n"
                 "END: }" STEP_ARGS(1));
}
template <int O, int K, int J> __device__ __forceinline__ void mma_h(float (&y)[128], uint64_t a, uint64_t b) { mma128_ss<O, 1, 0>(y, a + SL(K) * 2048 + O * 8 + 128 * J, b + SL(K) * 2048 + 2 * J, 1); }
template <int O, int K> __device__ __forceinline__ void half_step(float (&y)[128], uint64_t a, uint64_t b) { mma_h<O, K, 0>(y, a, b); mma_h<O, K, 1>(y, a, b); mma_h<O, K, 2>(y, a, b); mma_h<O, K, 3>(y, a, b); }
template <int R, int U> __device__ __forceinline__ void out_piece(float (&y)[128], const uint32_t (&dd)[16], uint32_t x0, uint32_t x1, float* op) {
    const int i = 64 * (R >> 1) + 8 * U + 2 * (R & 1);
    asm("mul.rn.bf16x2 %0, %0, %1;" : "+r"(x0) : "r"(dd[2 * U]));
    asm("mul.rn.bf16x2 %0, %0, %1;" : "+r"(x1) : "r"(dd[2 * U + 1]));
    asm volatile("st.global.v4.f32 [%0], {%1,%2,%3,%4};" ::"l"(op + (32 * (R & 1) + 16 * (R >> 1)) * 2048 + 16 * U),
                 "f"(y[i] + __uint_as_float(x0 << 16)), "f"(y[i + 1] + __uint_as_float(x0 & 0xffff0000u)),
                 "f"(y[i + 4] + __uint_as_float(x1 << 16)), "f"(y[i + 5] + __uint_as_float(x1 & 0xffff0000u)) : "memory");
}
template <int R, int U0> __device__ __forceinline__ void load_x4(uint32_t (&xx)[8], uint32_t xa) {
#pragma unroll
    for (int u = 0; u < 4; u++)
        asm volatile("ld.shared.v2.b32 {%0,%1}, [%2];" : "=r"(xx[2 * u]), "=r"(xx[2 * u + 1]) : "r"((xa ^ (u << 5)) + (3 - R) * 8192 + U0 * 1024) : "memory");
}
__device__ __forceinline__ Ring ring_at(uint32_t sb, int k) {
    Ring r;
    r.n = 0;
    r.full = sb + OFF_BAR + B_FULL;
    asm("mapa.shared::cluster.u32 %0, %1, %2;" : "=r"(r.rel) : "r"(sb + OFF_BAR + B_EMPTY), "r"((threadIdx.x >> 5) & 1));
    r.sig = __shfl_sync(~0u, threadIdx.x & 95, threadIdx.x) == 0;
    return r;
}

template <bool BY_SM> __global__ void __cluster_dims__(2, 1, 1) __launch_bounds__(512, 1)
fused_kernel(const __grid_constant__ CUtensorMap tmX, const __grid_constant__ CUtensorMap tmBre, const __grid_constant__ CUtensorMap tmBim,
             const __grid_constant__ CUtensorMap tmCre, const __grid_constant__ CUtensorMap tmCim, const __grid_constant__ CUtensorMap tmXd,
             const __grid_constant__ CUtensorMap tmUst,
             const __grid_constant__ CUtensorMap tmWr, const __grid_constant__ CUtensorMap tmWi, const __grid_constant__ CUtensorMap tmXa,
             const Params p) {
    extern __shared__ __align__(1024) uint8_t smraw[];
    asm volatile(".reg .pred pk, p0;");
    const int tid = TIDMAP, rank = blockIdx.x & 1;
    const uint32_t wi = __shfl_sync(~0u, smem_u32(smraw) + (tid >> 5), 0), sb = wi & ~15u, bars = sb + OFF_BAR;
    const int wg = (wi >> 2) & 3, w = wi & 3, lane = tid & 31, g = lane >> 2, q = lane & 3;
    if (wg != 3) asm volatile("barrier.cluster.arrive.relaxed.aligned; barrier.cluster.wait.aligned;" ::: "memory");
    else asm volatile("prefetch.tensormap [%0];" ::"l"(w == 0 ? &tmX : w == 1 ? &tmBre : &tmBim) : "memory");
    int role;
    {
        uint32_t T = blockIdx.x;
        if (BY_SM) asm("mov.u32 %0, %%smid;" : "=r"(T));
        T >>= 1;
        const uint32_t a = ((T - 32) * 37) >> 8;
        asm("{.reg .pred p; setp.lt.u32 p, %1, 62; selp.u32 %0, 4, -58, p; add.u32 %0, %0, %1;\n"
            "setp.lt.u32 p, %1, 60; selp.u32 %0, %2, %0, p; setp.lt.u32 p, %1, 32; selp.u32 %0, %3, %0, p;}"
            : "=&r"(role) : "r"(T), "r"(8 * (T - 31 - 7 * a) + 4 + a), "r"(8 * (T & 7) + (T >> 3)));
        role = 2 * role + rank;
    }
    const bool spare = role >= 128;
    const int tc = ((role >> 3) & 14) + rank, cb = (role >> 1) & 7;
    const int fb = role >> 5, fcb = role & 31, fpos = pos_of(fcb);
    const int nu = role == 128 ? 1 : (fcb || !role ? 2 : 0);

    if (wg == 3) {
        if (elect_one()) {
            const uint32_t b = bars + w * 8;
            STAMP5(57);
            mbar_init(b, 1);
            if (w < 2 && !spare) {
                mbar_expect_tx(b, 32768);
                tma5d(sb + w * 32768 + 16384, &tmX, w * 64, 0, 0, 0, tc, b);
                if (w == 0) { tma4d(sb, &tmBre, 0, 0, 0, cb * 4, b); tma4d(sb + 8192, &tmBim, 0, 0, 0, cb * 4, b); }
                STAMP5(58);
            }
#pragma unroll
            for (int o = 32; o < B_EPOCH; o += 32) mbar_init(b + o, o < B_EMPTY ? 1 : (o < B_STG ? 2 : (o < B_P3M ? 4 : 8)));
            asm volatile("fence.mbarrier_init.release.cluster;" ::: "memory");
        }
        __syncwarp();
        STAMP5(59);
        asm volatile("barrier.cluster.arrive.relaxed.aligned;" ::: "memory");
    }
    if (opaque32(wg) == 3) {
        asm volatile("setmaxnreg.dec.sync.aligned.u32 24;");
        asm volatile("barrier.cluster.wait.aligned;" ::: "memory");
        if (w == 0) {
            if (!spare && elect_one()) {
                STAMP(56);
#pragma unroll 1
                for (int k = 1; k < NST; k++) {
                    if (k >= 2) mbar_expect_tx(bars + B_FULL + k * 8, 32768);
                    tma4d_mc(sb + k * 32768 + rank * 8192, rank ? &tmBim : &tmBre, k * 64, 0, 0, cb * 4, bars + B_FULL + k * 8);
                    if (k >= 2) tma5d(sb + k * 32768 + 16384, &tmX, k * 64, 0, 0, 0, tc, bars + B_FULL + k * 8);
                }
#define RING_WAIT "mbarrier.try_wait.parity.shared::cta.b64 p, [fb + 256], ph; @p bra GO;\n" \
                  "WAIT: mbarrier.try_wait.parity.shared::cta.b64 p, [fb + 256], ph; add.u32 n, n, 1; setp.gt.or.u32 p, n, 32768, p; @!p bra WAIT;\nGO:\n"
#define RING_NEXT "pmevent 1; add.u32 o, o, 8; setp.eq.u32 p, o, 40; selp.u32 o, 0, o, p; @p xor.b32 ph, ph, 1; add.u32 fb, %1, o; shl.b32 t, o, 12; add.u32 da, %0, t;\n"
                asm volatile("{.reg .b32 o, k, kk, c2, da, db, fb, ph, n, t; .reg .pred p;\n"
                             "mov.b32 o, 0; mov.b32 k, 320; mov.b32 kk, 320; mov.b32 c2, 0; mov.b32 ph, 0; mov.b32 n, 0; mov.b32 fb, %1; mov.b32 da, %0; mov.b32 db, %2;\n"
                             "LOOP:\n" RING_WAIT
                             "cp.async.bulk.tensor.5d.shared::cluster.global.mbarrier::complete_tx::bytes [da], [%3, {kk,0,0,0,%5}], [fb];\n"
                             "cp.async.bulk.tensor.4d.shared::cluster.global.mbarrier::complete_tx::bytes.multicast::cluster [db], [%4, {kk,0,c2,%6}], [fb], %7;\n"
                             "mbarrier.arrive.expect_tx.shared::cta.b64 _, [fb], 32768;\n" RING_NEXT
                             "add.u32 db, %2, t; add.u32 k, k, 64; and.b32 kk, k, 1023; shr.u32 c2, k, 9; and.b32 c2, c2, 2; setp.ne.u32 p, k, 2048; @p bra LOOP;}"
                             ::"r"(sb + 16384), "r"(bars + B_FULL), "r"(sb + rank * 8192), "l"(&tmX), "l"(rank ? &tmBim : &tmBre), "r"(tc), "r"(cb * 4), "h"((uint16_t)3) : "memory");
                asm volatile("{.reg .b32 o, k, kk, da, db, fb, hb, ph, n, t; .reg .b64 m, src; .reg .pred p;\n"
                             "mov.b32 o, 16; mov.b32 k, 0; mov.b32 kk, 0; mov.b32 ph, 1; mov.b32 n, 0; add.u32 fb, %1, 16; add.u32 hb, %1, 72; add.u32 da, %0, 65536; add.u32 db, %2, 65536;\n"
                             "mov.b64 m, %3; mov.b64 src, %5;\n"
                             "GROUP: add.u32 t, %8, k;\n"
                             "OWN: mbarrier.try_wait.parity.shared::cta.b64 p, [t], 0; add.u32 n, n, 1; setp.gt.or.u32 p, n, 32768, p; @!p bra OWN;\n"
                             "LOOP:\n" RING_WAIT
                             "cp.async.bulk.shared::cluster.global.mbarrier::complete_tx::bytes [da], [src], 16384, [hb];\n"
                             "cp.async.bulk.tensor.5d.shared::cluster.global.mbarrier::complete_tx::bytes.multicast::cluster [db], [m, {kk,0,0,0,%6}], [fb], %7;\n"
                             "mbarrier.expect_tx.shared::cta.b64 [fb], 16384; mbarrier.arrive.expect_tx.shared::cta.b64 _, [hb], 16384;\n" RING_NEXT
                             "add.u32 db, %2, t; add.u64 src, src, 16384; sub.u64 m, %4, m; add.u32 k, k, 1; shl.b32 kk, k, 5; and.b32 kk, kk, 0x7c0;\n"
                             "and.b32 t, k, 1; mad.lo.u32 hb, t, 8, fb; add.u32 hb, hb, o; add.u32 hb, hb, 40;\n"
                             "and.b32 t, k, 7; setp.ne.u32 p, t, 0; @p bra LOOP; setp.ne.u32 p, k, 32; @p bra GROUP;}"
                             ::"r"(sb), "r"(bars + B_FULL), "r"(sb + 16384 + rank * 8192), "l"(&tmCre), "l"((uint64_t)&tmCre + (uint64_t)&tmCim),
                               "l"(g_H + (size_t)tc * 32 * 16384), "r"(cb * 8 + rank * 4), "h"((uint16_t)3), "r"(bars + B_HOWN) : "memory");
            }
        } else if (opaque32(w) == 1) {
            const unsigned ep = ld_rlx(g_epoch + role * 8) + 1;
            __syncwarp();
            if (elect_one()) {
                asm volatile("st.relaxed.gpu.global.u32 [%0], %1;" ::"l"(g_epoch + role * 8), "r"(ep) : "memory");
                asm volatile("st.shared.u32 [%0], %1;" ::"r"(bars + B_EPOCH), "r"(ep) : "memory");
                mbar_arrive(bars + B_EP);
            }
            int slot;
            const int kap = unit_of(role, 0, slot), kap1 = unit_of(role, 1, slot);
            uint32_t lph = 0;
            if (!spare) mbar_wait(bars + B_STGU, 0);
            STAMP(21);
            const int c0 = fb * 2048 + fpos * 64;
            if (elect_one()) {
                if (!spare) {
#pragma unroll 1
                    for (int r = 4; r < 8; r++) bulk_st(g_X + r * (32 * 16384) + c0 * 2, sb + OFF_P + r * 4096, 128);
                    tma2d_st(&tmUst, c0, 0, sb + OFF_P);
                    bulk_commit();
                    tma2d_st(&tmUst, c0, 64, sb + OFF_P + 8192);
                    bulk_commit();
                    if (UHINT == 1) asm volatile("cp.async.bulk.wait_group.read 1;" ::: "memory");
                    if (UHINT < 2) red_hint(g_cnt);
                }
                mbar_expect_tx(bars + B_FG, 8192);
                bulk_ld(sb + OFF_F, (const uint8_t*)g_tab + TAB_FG, 8192, bars + B_FG);
            }
            STAMP(40);
#pragma unroll 1
            for (int e = 0; e < 4; e++) {
                if (e >= 2) {
                    if (e == nu) {
                        mbar_wait(bars + B_WFREE, 0);
                        if (elect_one()) load_w_rows(sb + OFF_WD, &tmWr, &tmWi, kap1, bars + B_WD);
                    }
                    if (e - 2 < nu) mbar_wait(bars + B_STG, e & 1);
                    STAMPO(23, e - 2);
                    if (e == 3 && !spare && elect_one()) {
                        mbar_expect_tx(bars + B_FG, 8192);
                        bulk_ld(sb + OFF_F, (const uint8_t*)g_tab + TAB_G + fb * 8192, 8192, bars + B_FG);
                    }
                }
                const uint32_t tg = e < 2 ? lane * 128 + ((((lane >> 1) & 2) ^ (lane & 3)) << 4) + (lane >> 3) * 4 : lane * 64 + (lane & 8) * 4 + (lane & 2) * 8 + (lane & 4) * 2;
                if (spare) {
                    if (e == 1) {
                        wait_cnt(g_cnt, 128 * ep);
                        STAMP(42);
#pragma unroll 1
                        for (int n = 0; n < 4096; n++) {
                            if (elect_one()) {
                                mbar_expect_tx(bars + B_LD, 8 * 16384);
#pragma unroll 1
                                for (int r = 0; r < 8; r++) bulk_ld(sb + r * 16384, g_X + (size_t)r * (32 * 16384), 16384, bars + B_LD);
                            }
                            mbar_wait(bars + B_LD, n & 1);
                            bool ok = true;
#pragma unroll 1
                            for (int r = 0; r < 8; r++) ok &= tags_ok<4096>(sb + r * 16384 + tg, ep);
                            if (ok) break;
                        }
                        if (elect_one()) mbar_arrive(bars + B_RAW);
                    }
                } else {
                    const uint32_t dst = sb + OFF_P + (e & 1) * 16384;
                    wait_cnt(g_cnt + e * 32, 128 * ep);
                    STAMPO(41, e == 2 ? -12 : e);
#pragma unroll 1
                    for (int n = 0; n < 4096; n++) {
                        if (elect_one()) {
                            bulk_wait_read();
                            mbar_expect_tx(bars + B_LD, 16384);
                            bulk_ld(dst, g_X + (size_t)(e < 2 ? role + e * 128 : 254 + (fb * 32 + fpos) * 2 + e) * 16384, 16384, bars + B_LD);
                            if (U1POS == 0 && e + n == 0) { tma2d_st(&tmUst, c0, 128, dst + 16384); tma2d_st(&tmUst, c0, 192, dst + 24576); bulk_commit(); }
                        }
                        mbar_wait(bars + B_LD, lph);
                        if (!e) STAMP3(49);
                        lph ^= 1;
                        if (tags_ok<4096>(dst + tg, ep) & tags_ok<4096>(dst + tg + (e & 2) * 1024, ep) & tags_ok<0>(dst + (e == 3 ? (lane & 1) * 8192 + 32 : 0), ep)) break;
                    }
                    if (elect_one()) mbar_arrive(bars + B_IN + e * 8);
                }
                if (e < 2 && elect_one()) {
                    if (e) prefetch_w_rows(&tmWr, &tmWi, kap1);
                    else {
                        if (nu) load_w_rows(sb + OFF_WD, &tmWr, &tmWi, kap, bars + B_WD);
                        if (!spare) {
                            if (U1POS) { tma2d_st(&tmUst, c0, 128, sb + OFF_P + 16384); bulk_commit(); tma2d_st(&tmUst, c0, 192, sb + OFF_P + 24576); bulk_commit(); }
                            if (U1POS == 2) asm volatile("cp.async.bulk.wait_group.read 1;" ::: "memory"); else bulk_wait_read();
                            red_hint(g_cnt + 32);
                        }
                    }
                }
            }
            if (!spare) {
                mbar_wait(bars + B_HOWN + 8, 0);
#pragma unroll 1
                for (int r = 0; r < 4; r++) {
                    if (r == 3) mbar_wait(bars + B_P3M, 0);
                    if (elect_one()) {
                        if (r == 0) { mbar_expect_tx(bars + B_XD, 24576 + 256); mbar_expect_tx(bars + B_XD + 8, 8192); bulk_ld(sb + OFF_LAM, p.dsk + cb * 128, 256, bars + B_XD); }
                        tma4d(sb + OFF_F + (3 - r) * 8192, &tmXd, 0, tc * 128 + 32 * (r & 1) + 16 * (r >> 1), 0, cb * 2, bars + B_XD + (r == 3) * 8);
                    }
                    __nanosleep(PACE_X);
                }
            }
        } else {
            if (w == 2) {
                {
                    const int u = lane >> 4;
                    int slot;
                    const int r0 = unit_of(role, u, slot) + 512 * ((lane >> 1) & 3), r1 = (2048 - r0) & 2047, mir = (lane >> 3) & 1;
                    const unsigned short* wp = (const unsigned short*)((lane & 1) ? p.wi : p.wr);
                    const float a = bf2f(wp[r0 * 513 + mir * 512]), b = bf2f(wp[r1 * 513 + mir * 512]);
                    asm volatile("st.shared.f32 [%0], %1;" ::"r"(sb + OFF_WSP + u * 64 + (lane & 15) * 4), "f"(0.5f * ((lane & 1) ? (mir ? b - a : a - b) : a + b)) : "memory");
                }
                warp_arrive(bars + B_WSP);
            } else if (!spare) {
                if (XA_T0) __nanosleep(XA_T0);
#pragma unroll 1
                for (int i = 0; i < 8; i++) {
                    if (i >= XA_N0) __nanosleep(XA_PACE);
                    if (elect_one()) {
                        if (i == 0) mbar_expect_tx(bars + B_XIN, 32768);
                        tma3d(sb + OFF_F + i * 4096, &tmXa, fcb * 32, 0, 4 * i + fb, bars + B_XIN);
                    }
                }
            }
            if (!spare) {
                if (w == 2 && nu) {
                    int slot;
                    const int kap = unit_of(role, 0, slot);
                    mbar_wait(bars + WPFB, 0);
                    if (elect_one()) prefetch_w_rows(&tmWr, &tmWi, kap);
                }
                const unsigned ep = get_epoch(bars);
#define CNT_RETRY
#define CNT_ARG
                asm volatile("{.reg .b32 o, k, hb, fb, ca, m, ph, rph, n, t, v0, v1, v2, v3; .reg .b64 src; .reg .pred p, pe;\n"
                             "elect.sync _|pe, 0xffffffff; mov.b32 o, %0; shr.u32 k, %0, 3; sub.u32 k, k, 2; mov.b32 m, 0x107c0; mov.b32 rph, 0; mov.b32 n, 0;\n"
                             "bra NEXT;\n"
                             "LOOP: mbarrier.try_wait.parity.shared::cta.b64 p, [hb], ph; @p bra GO;\n"
                             "WAIT: mbarrier.try_wait.parity.shared::cta.b64 p, [hb], ph; add.u32 n, n, 1; setp.gt.or.u32 p, n, 32768, p; @!p bra WAIT;\n"
                             "GO: ld.shared.u32 v0, [ca]; ld.shared.u32 v1, [ca + 128]; ld.shared.u32 v2, [ca + 256]; ld.shared.u32 v3, [ca + 384];\n"
                             "lop3.b32 v0, v0, v1, %4, 0x7e; lop3.b32 v2, v2, v3, %4, 0x7e; lop3.b32 v0, v0, v2, 1, 0xa8; setp.eq.u32 p, v0, 0; vote.sync.all.pred p, p, -1; @p bra OK;\n"
                             CNT_RETRY "add.u32 n, n, 16; setp.gt.u32 p, n, 32768; @p bra OK;\n"
                             "shl.b32 t, o, 12; add.u32 t, t, %5; mad.wide.u32 src, k, 16384, %6;\n"
                             "@pe mbarrier.arrive.expect_tx.shared::cta.b64 _, [%7], 16384; @pe cp.async.bulk.shared::cluster.global.mbarrier::complete_tx::bytes [t], [src], 16384, [%7];\n"
                             "AGAIN: mbarrier.try_wait.parity.shared::cta.b64 p, [%7], rph; add.u32 n, n, 1; setp.gt.or.u32 p, n, 32768, p; @!p bra AGAIN;\n"
                             "xor.b32 rph, rph, 1; bra GO;\n"
                             "OK: @pe mbarrier.arrive.shared::cta.b64 _, [fb]; pmevent 1;\n"
                             "add.u32 o, o, 16; setp.ge.u32 p, o, 40; @p sub.u32 o, o, 40; add.u32 k, k, 2;\n"
                             "NEXT: shr.u32 m, m, 1; and.b32 ph, m, 1; add.u32 fb, %1, o; mad.lo.u32 hb, o, 2, %2; mad.lo.u32 ca, o, 4096, %3; setp.lt.u32 p, k, 32; @p bra LOOP;}"
                             ::"r"(8 * w), "r"(bars + B_FULL), "r"(bars + B_HL - 16 + w * 8), "r"(sb + (q >> 1) * 8192 + (q & 1) * 512 + g * 1040 + q * 4), "r"(ep),
                               "r"(sb), "l"(g_H + (size_t)tc * 32 * 16384), "r"(bars + B_HR - 16 + w * 8) CNT_ARG : "memory");
                if (w == 3) warp_arrive(bars + B_DONE);
            }
        }
    } else {
        STAMP(55);
        asm volatile("setmaxnreg.inc.sync.aligned.u32 152;");
        STAMP5(60);
        const int t7 = tid & 127, hf = wg - 1;
        const int mi = lane >> 3, gl = lane & 7;
        if (spare && wg != 2) {
            if (tid < 64) { const uint4 v = __ldg((const uint4*)((const uint8_t*)g_tab + TAB_PC) + tid); sts128(sb + OFF_LAM + tid * 16, v.x, v.y, v.z, v.w); }
            bar_sync(1, 256);
            mbar_wait(bars + B_RAW, 0);
            STAMP(0);
#pragma unroll 1
            for (int u = 0; u < nu; u++) {
                int slot;
                const int t = unit_of(role, u, slot) >> 5;
                const uint32_t off = (tid >> 2) * 128 + q * 16;
                float zr[16], zi[16];
#pragma unroll
                for (int k = 0; k < 16; k++) zr[k] = zi[k] = 0.f;
#pragma unroll 1
                for (int r = (t & 1) ? 0 : t >> 1; r < 8 - ((t & 1) ? 0 : (t >> 1) - 1); r += (t & 1) ? 1 : 8 - t) {
                    float4 c;
                    float a[8], b[8];
                    lds128f(sb + OFF_LAM + t * 128 + r * 16, c.x, c.y, c.z, c.w);
                    lds128f(sb + r * 16384 + off, a[0], a[1], a[2], a[3]);
                    lds128f(sb + r * 16384 + off + 64, b[0], b[1], b[2], b[3]);
                    lds128f(sb + r * 16384 + off + 8192, a[4], a[5], a[6], a[7]);
                    lds128f(sb + r * 16384 + off + 8192 + 64, b[4], b[5], b[6], b[7]);
#pragma unroll
                    for (int k = 0; k < 16; k++) {
                        const uint32_t ua = __float_as_uint(a[k >> 1]), ub = __float_as_uint(b[k >> 1]);
                        const float x = __uint_as_float((k & 1) ? ua & 0xffff0000u : ua << 16), y = __uint_as_float((k & 1) ? ub & 0xffff0000u : ub << 16);
                        zr[k] = fmaf(c.x, x, fmaf(c.z, y, zr[k]));
                        zi[k] = fmaf(c.y, x, fmaf(c.w, y, zi[k]));
                    }
                }
                const uint32_t dst = sb + OFF_P + u * 16384 + off;
#pragma unroll
                for (int k = 0; k < 16; k += 8) {
                    sts128(dst + k * 1024, pk(zr[k], zr[k + 1]), pk(zr[k + 2], zr[k + 3]), pk(zr[k + 4], zr[k + 5]), pk(zr[k + 6], zr[k + 7]));
                    sts128(dst + k * 1024 + 64, pk(zi[k], zi[k + 1]), pk(zi[k + 2], zi[k + 3]), pk(zi[k + 4], zi[k + 5]), pk(zi[k + 6], zi[k + 7]));
                }
                fence_async_sm();
                bar_sync(1, 256);
                if (tid == 0) mbar_arrive(bars + B_IN + u * 8);
                STAMPO(1, u);
            }
            return;
        }
        if (wg == 2 && !spare) {
            asm volatile("setmaxnreg.inc.sync.aligned.u32 176;");
            uint32_t f1[16];
            cf tw[8];
            if (TAB_T0) __nanosleep(TAB_T0);
            ldtab<4, 2048>(f1, TAB_F1 + t7 * 16);
            ldtab_cf<16>(tw, TAB_TW1 + (t7 >> 2) * 64);
            const uint32_t ep = get_epoch(bars);
            uint32_t a0 = sb + OFF_P + (8 * w + gl + 32 * (mi >> 1)) * 128 + (((((mi & 1) << 2) | (fpos & 3)) ^ gl) << 4);
            float acc[128];
            const uint64_t dx = opaque(mkdesc(sb + OFF_F, 4096, 512, 2));
            mbar_wait(bars + B_XIN, 0);
            STAMP(20);
            pinu(f1);
            wg_fence();
#pragma unroll
            for (int j = 0; j < 4; j++) {
                mma128_rs<0, 1>(acc, f1[4 * j], f1[4 * j + 1], f1[4 * j + 2], f1[4 * j + 3], dx + j * 64, j);
                mma128_rs<64, 1>(acc, f1[4 * j], f1[4 * j + 1], f1[4 * j + 2], f1[4 * j + 3], dx + 1024 + j * 64, j);
            }
            wg_commit();
            wg_wait<0>();
            pin(acc);
            pinu(f1);
#pragma unroll 1
            for (int h = 0;; h++) {
                const uint32_t tmask = 2 * q + h == fpos >> 2 ? ~1u : ~0u, tbit = ep & ~tmask;
#pragma unroll
                for (int cl = 0; cl < 2; cl++) {
                    c2 v[8];
#pragma unroll
                    for (int n = 0; n < 8; n++) {
                        const int i = 4 * (4 * n + cl);
                        v[n] = {{acc[i], acc[i + 2]}, {acc[i + 1], acc[i + 3]}};
                    }
                    dft8<true, YP1>(v, tw);
#pragma unroll
                    for (int r = 0; r < 8; r += 2) {
                        uint32_t o0 = pk(v[r].a.x, v[r].b.x), o1 = pk(v[r].a.y, v[r].b.y), o2 = pk(v[r + 1].a.x, v[r + 1].b.x), o3 = pk(v[r + 1].a.y, v[r + 1].b.y);
                        if (cl == 0) { o0 = (o0 & tmask) | tbit; o2 = (o2 & tmask) | tbit; }
                        stsm4((a0 ^ (cl << 4)) + r * 4096, o0, o1, o2, o3);
                    }
                }
                if (h) break;
                a0 ^= 32;
#pragma unroll
                for (int n = 0; n < 8; n++) {
                    asm volatile("mov.b32 %0, %8; mov.b32 %1, %9; mov.b32 %2, %10; mov.b32 %3, %11; mov.b32 %4, %12; mov.b32 %5, %13; mov.b32 %6, %14; mov.b32 %7, %15; pmevent 1;"
                                 : "=&f"(acc[16 * n]), "=&f"(acc[16 * n + 1]), "=&f"(acc[16 * n + 2]), "=&f"(acc[16 * n + 3]), "=&f"(acc[16 * n + 4]), "=&f"(acc[16 * n + 5]), "=&f"(acc[16 * n + 6]), "=&f"(acc[16 * n + 7])
                                 : "f"(acc[16 * n + 8]), "f"(acc[16 * n + 9]), "f"(acc[16 * n + 10]), "f"(acc[16 * n + 11]), "f"(acc[16 * n + 12]), "f"(acc[16 * n + 13]), "f"(acc[16 * n + 14]), "f"(acc[16 * n + 15]));
                }
            }
            fence_async_sm();
            warp_arrive(bars + B_STGU);
            bar_sync(3, 128);
            asm volatile("setmaxnreg.dec.sync.aligned.u32 152;");
            bar_arrive(7, 256);
        }
        if (wg == 1) {
            if (LAM_T0) __nanosleep(LAM_T0);
            const int cl = tid & 127, ch = (cl >> 6) * 512 + ((cl >> 3) & 1) * 256 + cb * 32 + ((cl >> 4) & 3) * 8 + (cl & 7);
            const float lr = bf2f(*(const unsigned short*)padd(p.lre, 2 * ch)), li = bf2f(*(const unsigned short*)padd(p.lim, 2 * ch));
            const float dt = __bfloat162float(__float2bfloat16(expf(bf2f(*(const unsigned short*)padd(p.ldt, 2 * ch)))));
            const float an = dt * li, th = an * 0.318309873342514f;
            float sn, cs, inv;
            sincospif(fmaf(rintf(0.5f * th), -2.f, th) + fmaf(an, 1.2841276653e-8f, fmaf(an, 0.318309873342514f, -th)), &sn, &cs);
            const float ex = expf(dt * lr), br = ex * cs, bi = ex * sn;
            asm("rcp.approx.f32 %0, %1;" : "=f"(inv) : "f"(lr * lr + li * li));
            inv += inv;
            const float cr = ((br - 1.f) * lr + bi * li) * inv, ci = (bi * lr - (br - 1.f) * li) * inv;
            sts128(sb + OFF_LAM + cl * 16, __float_as_uint(br), __float_as_uint(-bi), __float_as_uint(cr), __float_as_uint(-ci));
            mbar_wait(bars + B_EP, 0);
            bar_sync(8, 128);
            if (tid == 128) mbar_arrive(bars + B_LAM);
        }
        if (wg != 2) {
        if (wg == 0) bar_sync(4, 128); else bar_sync(7, 256);
        asm volatile("setmaxnreg.inc.sync.aligned.u32 160;");
        if (wg == 0) bar_sync(4, 128);
        float d[128];
        if (wg == 1) bar_sync(1, 256);
        STAMPW(0, 10);
        Ring rg = ring_at(sb, role * 66 + wg * 16);
        cf lam[2];
        unsigned ep;
        mbar_wait_fast(rg.full + 8 * wg, wg);
        gemm1(d, rg, ring_desc(sb, 0, 16, 1), ring_desc(sb, 16384, 16, 1), wg);
        const uint32_t lama = sb + OFF_LAM + wg * 1024 + w * 256 + (fresh_lane() & 28) * 4;
        mbar_wait_fast(bars + B_LAM, 0);
        lam[0] = lds_cf(lama); lam[1] = lds_cf(lama + 128);
        asm volatile("ld.shared.u32 %0, [%1];" : "=r"(ep) : "r"(bars + B_EPOCH) : "memory");
        asm volatile("setmaxnreg.inc.sync.aligned.u32 176;");
        cf L[2] = {lam[0], lam[1]};
#pragma unroll
        for (int i = 0; i < 4; i++) { L[0] = csq(L[0]); L[1] = csq(L[1]); }
        asm volatile("" : "+f"(L[0].x), "+f"(L[0].y), "+f"(L[1].x), "+f"(L[1].y)::"memory");
        wg_wait<0>();
        ring_release(rg, 8 * wg);
        pin(d);
        STAMPW(1, 11);
        {
            const int lane = fresh_lane(), g = lane >> 2, q = lane & 3, mi = lane >> 3, gl = lane & 7;
            cf f[2], fb2[2];
#pragma unroll
            for (int i = 0; i < 17; i++) {
#pragma unroll
                for (int h = 0; h < 2; h++) {
                    const int r = 4 * (i >> 1) + 2 * h + (i & 1), r2 = 32 + 4 * ((i - 1) >> 1) + 2 * h + ((i - 1) & 1);
                    if (i < 16) f[h] = i ? cfma(lam[h], f[h], {d[r], -d[64 + r]}) : cf{d[r], -d[64 + r]};
                    if (i > 0) fb2[h] = i > 1 ? cfma(lam[h], fb2[h], {d[r2], -d[64 + r2]}) : cf{d[r2], -d[64 + r2]};
                    if (i && (h || !(YS & 8))) YIELD_S1();
                }
            }
            const uint8_t* cbase = (const uint8_t*)g_carry + (tc * 16 + wg * 8 + cb) * 512 + w * 64;
            const uint8_t* cptr = padd(cbase, g * 8);
            const unsigned tag = ep & 15u;
#pragma unroll
            for (int h = 0; h < 2; h++) { f[h] = cfma(L[h], f[h], fb2[h]); L[h] = csq(L[h]); }
            cf s0[2], s1[2], s2[2];
#pragma unroll
            for (int h = 0; h < 2; h++) {
                s0[h] = {__shfl_sync(~0u, f[h].x, 0, 4), __shfl_sync(~0u, f[h].y, 0, 4)};
                s1[h] = {__shfl_sync(~0u, f[h].x, 1, 4), __shfl_sync(~0u, f[h].y, 1, 4)};
                s2[h] = {__shfl_sync(~0u, f[h].x, 2, 4), __shfl_sync(~0u, f[h].y, 2, 4)};
            }
#pragma unroll
            for (int h = 0; h < 2; h++) {
                s1[h] = cfma(L[h], s0[h], s1[h]);
                s2[h] = cfma(L[h], s1[h], s2[h]);
                f[h] = cfma(L[h], s2[h], f[h]);
                asm volatile("{.reg .pred p; .reg .b64 a; setp.eq.u32 p, %3, 3; mov.b64 a, {%1,%2}; @p st.relaxed.gpu.global.b64 [%0], a;}" ::"l"(cptr + h * 256),
                             "r"((__float_as_uint(f[h].x) & ~15u) | tag), "f"(f[h].y), "r"(q) : "memory");
            }
            STAMPX(2, 12);
            cf gam = lds_cf(lama + 8);
            cf st = csel(q & 2, csel(q & 1, s2[0], s1[0]), csel(q & 1, s0[0], {0.f, 0.f}));
            const cf st1 = csel(q & 2, csel(q & 1, s2[1], s1[1]), csel(q & 1, s0[1], {0.f, 0.f}));
            cptr = padd(cbase - 4 * 8192, (3 - mi) * 8192 + gl * 8);
            const int nprev = tc - 1 - mi;
            const uint8_t* hptr = padd(g_H + (size_t)(tc * 32 + wg * 16 + (cb & 6)) * 16384 + ((cb & 1) * 4 + w) * 1024, g * 64 + ((q ^ (g >> 1)) << 4));
            const uint32_t hm = 4 * (g & 1) + (q ^ (g >> 1)) == (cb & 1) * 4 + w ? ~1u : ~0u;
            float u[64];
            uint64_t fv[4] = {tag, tag, tag, tag};
            prescale<0>(u, d, gam);
            gather(fv, cptr, nprev);
#pragma unroll 1
            for (int h = 0;; h++) {
                const cf L2 = csq(L[0]), M = csq(L2);
                cf M4 = csq(csq(M));
                M4 = {__shfl_sync(~0u, M4.x, 4 * gl), __shfl_sync(~0u, M4.y, 4 * gl)};
                cf lq = cmul(gam, cmul(csel(q & 1, L[0], {1.f, 0.f}), csel(q & 2, L2, {1.f, 0.f})));
                st = cmul(gam, st);
                asm volatile("pmevent 1;" : "+f"(lq.x), "+f"(lq.y), "+f"(st.x), "+f"(st.y));
#pragma unroll 1
                for (unsigned n = 0; __any_sync(~0u, (((uint32_t)fv[0] ^ tag) | ((uint32_t)fv[1] ^ tag) | ((uint32_t)fv[2] ^ tag) | ((uint32_t)fv[3] ^ tag)) & 15u) && n < SPIN_LIMIT; n++) gather(fv, cptr, nprev);
                if (!h) STAMPX(53, 54);
                cf P = as_cf(fv[3]), pj[4];
#pragma unroll
                for (int a = 2; a >= 0; a--) P = cfma(M4, P, as_cf(fv[a]));
                cptr += 256;
                asm volatile("" : "+f"(P.x), "+f"(P.y)::"memory");
                gather(fv, cptr, h ? -1 : nprev);
#pragma unroll
                for (int j = 3; j >= 0; j--) pj[j] = {__shfl_sync(~0u, P.x, g + 8 * j), __shfl_sync(~0u, P.y, g + 8 * j)};
                st = cfma(lq, cfma(M, cfma(M, cfma(M, pj[3], pj[2]), pj[1]), pj[0]), st);
                if (!h) STAMPX(3, 13);
                uint32_t keep = sb >> 28;
                scan2(u, lam[0], st, hptr, hm, ep & ~hm, keep);
                warp_arrive(bars + B_HOWN + wg * 16 + h * 8 + keep);
                if (h) break;
                STAMPW(4, 14);
                lds128f(lama + 128, lam[0].x, lam[0].y, gam.x, gam.y);
                st = st1;
                L[0] = L[1];
                hptr += 8 * 16384;
                prescale<1>(u, d, gam);
            }
            STAMPW(5, 15);
        }
        if (wg == 0) bar_sync(4, 128); else bar_sync(8, 128);
        if (wg == 0) {
            asm volatile("setmaxnreg.dec.sync.aligned.u32 160;");
            float y[128];
            rg = ring_at(sb, role * 66 + 32);
            STAMP(6);
            bar_sync(2, 256);
            STAMP(7);
            mbar_wait_fast(rg.full + SL(32) * 8, PH(32));
            const uint64_t dA = ring_desc(sb, 0, 512, 2), dB = ring_desc(sb, 16384, 16, 1);
            gemm2(y, rg, dA, dB, 0);
            asm volatile("setmaxnreg.inc.sync.aligned.u32 184;");
            const int lane = fresh_lane(), g = lane >> 2, q = lane & 3;
            const int pg = 2 * (g & 3) + (g >> 2);
            float* op = (float*)padd(p.out + (size_t)(tc * 128 + 64 * (w & 1) + 8 * (w >> 1)) * 2048 + 1024 + cb * 128, pg * 8192 + q * 16);
            const uint32_t xa = sb + OFF_F + (16 * (w & 1) + 8 * (w >> 1) + pg) * 128 + (((q >> 1) ^ pg) << 4) + (q & 1) * 8;
#define HALF0(k) wg_fence(); peek(k < 63 ? rg.full + SL(k + 1) * 8 : bars + B_XD, PH(k + 1)); half_step<0, k>(y, dA, dB); wg_commit(); peek_wait(k < 63 ? rg.full + SL(k + 1) * 8 : bars + B_XD, PH(k + 1), rg.n);
            HALF0(60) HALF0(61) HALF0(62) HALF0(63)
            const uint64_t dB2 = ring_desc(sb >> 1, 16384, 16, 1);
            uint32_t xa0[8], xa1[8], dd[16];
#pragma unroll
            for (int i = 0; i < 8; i++) asm volatile("ld.shared.v2.b32 {%0,%1}, [%2];" : "=r"(dd[2 * i]), "=r"(dd[2 * i + 1]) : "r"(sb + OFF_LAM + q * 8 + 32 * i) : "memory");
            load_x4<0, 0>(xa0, xa);
            wg_fence();
            half_step<64, 64 - SKEW>(y, dA, dB2);
            wg_commit();
            wg_wait<1>();
#pragma unroll
            for (int i = 0; i < 64; i++) asm volatile("" : "+f"(y[i])::"memory");
            STAMP(16);
#define MM(n) if (4 + (n) < 4 * SKEW) { wg_fence(); mma_h<64, 65 - SKEW + (n) / 4, (n) % 4>(y, dA, dB2); mma_h<64, 65 - SKEW + (n) / 4, (n) % 4 + 1>(y, dA, dB2); }
#define OUT4(R, U, X, n) out_piece<R, U>(y, dd, X[0], X[1], op); MM(n) out_piece<R, U + 1>(y, dd, X[2], X[3], op); MM(n + 2) \
                         out_piece<R, U + 2>(y, dd, X[4], X[5], op); MM(n + 4) out_piece<R, U + 3>(y, dd, X[6], X[7], op); MM(n + 6)
            load_x4<0, 4>(xa1, xa);
            OUT4(0, 0, xa0, 0)
            load_x4<1, 0>(xa0, xa);
            OUT4(0, 4, xa1, 8)
            wg_commit();
            load_x4<1, 4>(xa1, xa);
            OUT4(1, 0, xa0, 16)
            load_x4<2, 0>(xa0, xa);
            OUT4(1, 4, xa1, 16)
            STAMP(18);
            wg_wait<0>();
#pragma unroll
            for (int i = 64; i < 128; i++) asm volatile("" : "+f"(y[i])::"memory");
            STAMP(8);
            load_x4<2, 4>(xa1, xa);
            mbar_wait_fast(bars + B_XD + 8, 0);
            OUT4(2, 0, xa0, 16)
            load_x4<3, 0>(xa0, xa);
            OUT4(2, 4, xa1, 16)
            load_x4<3, 4>(xa1, xa);
            OUT4(3, 0, xa0, 16)
            OUT4(3, 4, xa1, 16)
            STAMP(9);
            return;
        }
        asm volatile("setmaxnreg.dec.sync.aligned.u32 152;");
        } else {
        if (nu) {
            constexpr int Y = YP2;
            cf T[8];
            ldtab_cf<2048>(T, TAB_T + t7 * 16);
            const uint32_t ep = get_epoch(bars);
            const int ka = pos_of(t7 >> 2);
            asm volatile("setp.eq.u32 p0, %0, 0;" ::"r"(__shfl_sync(~0u, t7, lane)));
            mbar_wait(bars + B_WSP, 0);
            mbar_wait(bars + B_FG, 0);
            uint32_t wd[4], wm[4], vo[32];
            const uint8_t* vp;
            int slot;
            const int kap0 = unit_of(role, 0, slot), al = 2 * kap0;
            const int kap1 = __shfl_sync(~0u, unit_of(role, 1, slot), 0);
            slot = __shfl_sync(~0u, slot, 0);
            cf be1 = twid(kap0 + 512 * q, 2048), be2 = csq(be1), be3 = cmul(be1, be2);
#pragma unroll
            for (int j = 0; j < 4; j++) {
                wd[j] = sb + OFF_WD + ((j + q) & 3) * WPITCH + (al & 15) + 2 * ka + 64 * q;
                wm[j] = sb + OFF_WM + (((role ? 3 : 4) - j - q) & 3) * WPITCH + (-al & 15) + 1024 - 2 * ka - 64 * q;
                wd[j] = __shfl_sync(~0u, wd[j], lane);
            }
#pragma unroll 1
            for (int u = 0; u < nu; u++) {
                const uint32_t buf = sb + OFF_P + u * 16384;
                float acc[64], za[32], zb[32], ya[32], yb[32], vv[64];
                const uint64_t dF = opaque(mkdesc(sb + OFF_F, 16, 1024, 1)), dB = opaque(mkdesc(buf, 4096, 512, 2));
                mbar_wait(bars + B_IN + u * 8, 0);
                if (!role) {
                    const uint32_t z = buf + w * 1024 + (fresh_lane() >> 2) * 128 + 64 + (fresh_lane() & 3) * 16;
#pragma unroll
                    for (int i = 0; i < 4; i++) sts128(z + i * 4096, 0, 0, 0, 0);
                    fence_async_sm();
                    bar_sync(3, 128);
                }
                STAMP3(22);
                wg_fence();
#pragma unroll
                for (int j = 0; j < 4; j++) mma128_ss<0, 0, 1>(acc, dF + j * 2, dB + j * 64, j);
                wg_commit();
                const bool pv = u && (role || !(fresh_lane() & 4));
                if (u) {
                    warp_arrive(bars + B_STG);
#pragma unroll
                    for (int k = 0; k < VS0; k++) store_v(vo, vp, k, pv);
                    if (!role) { const uint32_t t = wm[0]; wm[0] = wm[1]; wm[1] = wm[2]; wm[2] = wm[3]; wm[3] = t; }
                }
                STAMP3(39);
                wg_wait<0>();
                pin(acc);
                STAMP3(30);
                uint32_t af[16], ag[16];
#pragma unroll
                for (int k = 0; k < 8; k++) {
                    uint32_t(&o)[16] = k < 4 ? af : ag;
                    const int c = k & 3;
#pragma unroll
                    for (int b = 0; b < 2; b++) {
                        const int i = 4 * (4 * ((k >> 2) * 2 + b) + c);
                        c2 x = mul2(c2{{acc[i], acc[i + 2]}, {acc[i + 1], acc[i + 3]}}, c2{T[2 * c], T[2 * c + 1]});
                        fin<Y>(x);
                        o[4 * c + b] = pk(x.a.x, x.a.y);
                        o[4 * c + 2 + b] = pk(x.b.x, x.b.y);
                    }
                    asm volatile("" : "+r"(o[4 * c]), "+r"(o[4 * c + 1]), "+r"(o[4 * c + 2]), "+r"(o[4 * c + 3])::"memory");
                    wg_fence();
                    mma64_rs<0>(k < 4 ? za : zb, o[4 * c], o[4 * c + 1], o[4 * c + 2], o[4 * c + 3], dF + c * 2, c);
                    if (k < 16 - VS0) store_v(vo, vp, VS0 + k, pv);
                }
                wg_commit();
                hint_v(g_cnt + 64, u * role);
                STAMP3(31);
                mbar_wait(bars + B_WD, u & 1);
                uint32_t wr[16];
#pragma unroll
                for (int i = 0; i < 16; i++) wr[i] = lds16(wd[i >> 2] + 256 * ((i >> 1) & 1) + (i & 1) * 4 * WPITCH);
                wg_wait<0>();
                pin(za);
                pin(zb);
                pinu(af);
                pinu(ag);
                STAMP3(32);
#pragma unroll
                for (int jb = 0; jb < 4; jb++) {
                    const int i = 8 * jb;
                    c2 s0 = {{za[i], za[i + 4]}, {za[i + 1], za[i + 5]}}, s2 = {{za[i + 2], za[i + 6]}, {za[i + 3], za[i + 7]}};
                    c2 s1 = {{zb[i], zb[i + 4]}, {zb[i + 1], zb[i + 5]}}, s3 = {{zb[i + 2], zb[i + 6]}, {zb[i + 3], zb[i + 7]}};
                    s2 = mul2(s2, be1);
                    fin<Y>(s2);
                    bfly_tw<Y>(s0, s1, be2, s2, s3, be3);
                    bfly<Y>(s0, s2); bfly_mi<Y>(s1, s3);
                    c2 W[4];
#pragma unroll
                    for (int j = 0; j < 4; j++) {
                        W[j] = {{__uint_as_float(wr[4 * j] << 16), __uint_as_float(wr[4 * j + 1] << 16)}, {__uint_as_float(wr[4 * j + 2] << 16), __uint_as_float(wr[4 * j + 3] << 16)}};
                        if ((jb & 1) == 0)
                            asm volatile("@p0 ld.shared.v2.f32 {%0,%1}, [%2];" : "+f"(W[j].a.x), "+f"(W[j].a.y) : "r"(sb + OFF_WSP + u * 64 + jb * 16 + j * 8));
                    }
                    if (jb < 3) {
#pragma unroll
                        for (int k = 0; k < 16; k++) {
                            const int e = (k >> 1) & 1, pl = (k & 1) * 4 * WPITCH;
                            wr[k] = jb == 0 ? lds16(wd[k >> 2] + 512 + 256 * e + pl) : lds16(wm[k >> 2] - 512 * (jb - 1) - 256 * e + pl);
                        }
                    }
                    if (jb >= 2) {
#pragma unroll
                        for (int j = 0; j < 4; j++) { W[j].a.y = -W[j].a.y; W[j].b.y = -W[j].b.y; }
                    }
                    s0 = mul2(s0, W[0]); fin<Y>(s0);
                    s1 = mul2(s1, W[1]); fin<Y>(s1);
                    bfly_tw<Y>(s0, s2, W[2], s1, s3, W[3]);
                    bfly<Y>(s0, s1); bfly_mi<Y>(s2, s3);
                    af[4 * jb] = pk(s0.a.x, s0.b.x); af[4 * jb + 1] = pk(s3.a.x, s3.b.x); af[4 * jb + 2] = pk(s0.a.y, s0.b.y); af[4 * jb + 3] = pk(s3.a.y, s3.b.y);
                    ag[4 * jb] = pk(s1.a.x, s1.b.x); ag[4 * jb + 1] = pk(s2.a.x, s2.b.x); ag[4 * jb + 2] = pk(s1.a.y, s1.b.y); ag[4 * jb + 3] = pk(s2.a.y, s2.b.y);
                }
                pinu(af);
                pinu(ag);
                warp_arrive(bars + B_WFREE);
                wg_fence();
#pragma unroll
                for (int j = 0; j < 4; j++) mma64_rs<1>(ya, af[4 * j], af[4 * j + 1], af[4 * j + 2], af[4 * j + 3], dF + j * 128, j);
                wg_commit();
#pragma unroll
                for (int j = 0; j < 4; j++) mma64_rs<1>(yb, ag[4 * j], ag[4 * j + 1], ag[4 * j + 2], ag[4 * j + 3], dF + j * 128, j);
                wg_commit();
                STAMP3(33);
                {
                    const uint32_t a0 = buf + (mi & 1) * 4096 + (16 * w + 8 * (mi >> 1) + gl) * 64 + ((gl >> 1) << 4);
#pragma unroll
                    for (int h = 0; h < 2; h++) {
                        if (h == 0) { wg_wait<1>(); pin(ya); pinu(af); STAMP3(34); } else { wg_wait<0>(); pin(yb); pinu(ag); }
                        const float(&yy)[32] = h ? yb : ya;
#pragma unroll
                        for (int c = 0; c < 4; c++) {
                            const int i = 8 * ((c + 2 * h) & 3), k = 8 * ((c + 2 * h + 1) & 3) + 2;
                            c2 x = {cmulc({yy[i], yy[i + 1]}, T[2 * c]), cmulc({yy[k], yy[k + 1]}, T[2 * c])};
                            fin<Y>(x);
                            c2 y = {cmulc({yy[i + 4], yy[i + 5]}, T[2 * c + 1]), cmulc({yy[k + 4], yy[k + 5]}, T[2 * c + 1])};
                            fin<Y>(y);
                            stsm4((a0 ^ (c << 4)) + h * 8192, pk(x.a.x, y.a.x), pk(x.b.x, y.b.x), pk(x.a.y, y.a.y), pk(x.b.y, y.b.y));
                        }
                    }
                }
                STAMP3(38);
                fence_async_sm();
                bar_sync(3, 128);
                wg_fence();
#pragma unroll
                for (int j = 0; j < 4; j++) mma128_ss<0, 1, 1>(vv, dF + j * 128, dB + j * 64, j);
                wg_commit();
                STAMP3(35);
                const int lane = fresh_lane(), g = lane >> 2, q = lane & 3;
                vp = padd(g_X + (4 << 20) + w * (8 * 32768) + (role ? u : 1) * 16384 + slot * 64,
                                         (g >> 1) * 32768 + (role ? g & 1 : u) * 32 + (((q ^ (slot >> 1)) & 1) << 4) + (q >> 1) * 8);
                const uint32_t tmask = (((g & 1) == ((slot >> 3) & 1) || !role) && q == ((slot >> 1) & 2)) ? ~1u : ~0u, tbit = ep & ~tmask;
                be1 = twid(kap1 + 512 * q, 2048); be2 = csq(be1); be3 = cmul(be1, be2);
                asm volatile("pmevent 1;" : "+f"(be1.x), "+f"(be1.y), "+f"(be2.x), "+f"(be2.y), "+f"(be3.x), "+f"(be3.y), "+l"(vp)::"memory");
                wg_wait<0>();
                pin(vv);
                STAMP3(36);
#pragma unroll
                for (int k = 0; k < 16; k++) {
                    const int i = 8 * (k >> 1) + 2 * (k & 1);
                    vo[2 * k] = (pk(vv[i], vv[i + 1]) & tmask) | tbit;
                    vo[2 * k + 1] = pk(vv[i + 4], vv[i + 5]);
                }
                pinu(vo);
            }
            warp_arrive(bars + B_STG);
            const bool odd = fresh_lane() & 4;
#pragma unroll
            for (int k = 0; k < 16; k++) {
                if (k == VPOS) hint_v(g_cnt + 32 + nu * 32, 1);
                store_v(vo, vp, k, role || odd == (k >= 4));
            }
        }
        if (spare) return;
        }
        {
            constexpr int Y = YP3;
            uint32_t sp[8];
            cf tw[8];
            ldtab<2, 2048>(sp, TAB_SP + fb * 4096 + t7 * 16);
            ldtab_cf<16>(tw, TAB_TW3 + fb * 2048 + (t7 >> 2) * 64);
            const uint64_t dF = opaque(mkdesc(sb + OFF_F, 16, 1024, 1)), dB = opaque(mkdesc(sb + OFF_P + hf * 8192, 1024, 256, 3));
            const uint8_t* op = padd(p.out + (1024 + fb) * 2048 + fcb * 32 + hf * 16, (t7 >> 2) * 32768 + (q >> 1) * 16 + (q & 1) * 32);
            float acc[64], out[64];
            mbar_wait(bars + B_IN + 24, 0);
            mbar_wait(bars + B_FG, 1);
            STAMP(25);
            pinu(sp);
            wg_fence();
#pragma unroll
            for (int j = 0; j < 4; j++) {
                const uint64_t db = dB + (j >> 1) * 1024 + (j & 1) * 32;
                mma112_ss(acc, dF + j * 2, db + 64, j);
                if (j & 1) mma16_rs(acc, 0u, sp[2 * j], 0u, sp[2 * j + 1], db, 1);
                else mma16_rs(acc, sp[2 * j], 0u, sp[2 * j + 1], 0u, db, j);
            }
            wg_commit();
            wg_wait<0>();
            pin(acc);
            pinu(sp);
            warp_arrive(bars + B_P3M);
#pragma unroll
            for (int cl = 0; cl < 2; cl++) {
                c2 z[8];
#pragma unroll
                for (int n = 0; n < 8; n++) {
                    const int i = 4 * (2 * n + cl);
                    z[n] = {{acc[i], acc[i + 2]}, {acc[i + 1], acc[i + 3]}};
                }
                z[0] = {{z[0].a.x + z[0].a.y, z[0].a.x - z[0].a.y}, {z[0].b.x + z[0].b.y, z[0].b.x - z[0].b.y}};
                z[4] = mul2(z[4], tw[4]);
                fin<Y>(z[0], z[4]);
#pragma unroll
                for (int n = 1; n < 4; n++) {
                    const cf iw = n == 1 ? cf{0.38268343236508977f, 0.92387953251128674f}
                                         : (n == 2 ? cf{0.70710678118654752f, 0.70710678118654752f} : cf{0.92387953251128674f, 0.38268343236508977f});
                    c2 y = mul2(z[n], tw[n]);
                    fin<Y>(y);
                    const cf t = {tw[8 - n].x, -tw[8 - n].y};
                    c2 E = fma2(c2{{z[8 - n].a.x, -z[8 - n].a.y}, {z[8 - n].b.x, -z[8 - n].b.y}}, t, y);
                    fin<Y>(E);
                    z[n] = fma2(twm2(y, E), iw, E);
                    fin<Y>(z[n]);
                    z[8 - n] = {{fmaf(2.f, E.a.x, -z[n].a.x), fmaf(-2.f, E.a.y, z[n].a.y)}, {fmaf(2.f, E.b.x, -z[n].b.x), fmaf(-2.f, E.b.y, z[n].b.y)}};
                }
                dft8<false, Y>(z, tw);
#pragma unroll
                for (int m = 0; m < 8; m++) {
                    out[8 * m + 2 * cl] = z[m].a.x; out[8 * m + 2 * cl + 1] = z[m].b.x;
                    out[8 * m + 4 + 2 * cl] = z[m].a.y; out[8 * m + 5 + 2 * cl] = z[m].b.y;
                }
            }
            STAMP(26);
#pragma unroll
            for (int m = 0; m < 16; m++) {
                asm volatile("st.global.v4.f32 [%0], {%1,%2,%3,%4};" ::"l"(op + (m - 8) * (1 << 20)), "f"(out[4 * m]), "f"(out[4 * m + 1]), "f"(out[4 * m + 2]), "f"(out[4 * m + 3]) : "memory");
                if (PACE_O && m < 15 && m % PACE_ON == PACE_ON - 1)
                    asm volatile("{.reg .pred p; mbarrier.test_wait.parity.shared::cta.b64 p, [%0], 0; @!p nanosleep.u32 %1;}" ::"r"(bars + B_DONE), "n"(PACE_O) : "memory");
            }
            STAMP(27);
        }
    }
}

typedef CUresult (*EncodeFn)(CUtensorMap*, CUtensorMapDataType, cuuint32_t, void*, const cuuint64_t*, const cuuint64_t*, const cuuint32_t*,
                             const cuuint32_t*, CUtensorMapInterleave, CUtensorMapSwizzle, CUtensorMapL2promotion, CUtensorMapFloatOOBfill);

static CUtensorMap make_map(EncodeFn enc, const void* ptr, int rank, const cuuint64_t* dims, const cuuint64_t* strides, const cuuint32_t* box,
                            CUtensorMapSwizzle swz, CUtensorMapL2promotion promo, CUtensorMapDataType dt = CU_TENSOR_MAP_DATA_TYPE_BFLOAT16) {
    CUtensorMap m;
    const cuuint32_t es[5] = {1, 1, 1, 1, 1};
    enc(&m, dt, rank, const_cast<void*>(ptr), dims, strides, box, es, CU_TENSOR_MAP_INTERLEAVE_NONE, swz, promo,
        CU_TENSOR_MAP_FLOAT_OOB_FILL_NONE);
    return m;
}

extern "C" void kernel_launch(void* const* d_in, const int* in_sizes, int n_in, void* d_out, int out_size) {
    void* fn = nullptr;
    cudaDriverEntryPointQueryResult qr;
    cudaGetDriverEntryPoint("cuTensorMapEncodeTiled", &fn, cudaEnableDefault, &qr);
    EncodeFn enc = (EncodeFn)fn;
    void* pX;
    cudaGetSymbolAddress(&pX, g_X);
    const CUtensorMapL2promotion P256 = CU_TENSOR_MAP_L2_PROMOTION_L2_256B, P0 = CU_TENSOR_MAP_L2_PROMOTION_NONE;

    const cuuint64_t dX[5] = {1024, 2, 4, 16, 16}, sX[4] = {2048, 32 * 2048, 2 * 2048, 128 * 2048};
    const cuuint32_t bX[5] = {64, 2, 4, 16, 1};
    CUtensorMap tmX = make_map(enc, d_in[3], 5, dX, sX, bX, CU_TENSOR_MAP_SWIZZLE_128B, P256);
    const cuuint64_t dXd[4] = {64, 2048, 2, 16}, sXd[3] = {2048, 64 * 2048, 128};
    const cuuint32_t bXd[4] = {64, 16, 2, 2};
    CUtensorMap tmXd = make_map(enc, d_in[3], 4, dXd, sXd, bXd, CU_TENSOR_MAP_SWIZZLE_128B, P256);
    const cuuint64_t dB[4] = {1024, 8, 4, 32}, sB[3] = {2048, 256 * 2048, 8 * 2048};
    const cuuint32_t bB4[4] = {64, 8, 2, 4};
    CUtensorMap tmBre = make_map(enc, d_in[6], 4, dB, sB, bB4, CU_TENSOR_MAP_SWIZZLE_128B, P256);
    CUtensorMap tmBim = make_map(enc, d_in[7], 4, dB, sB, bB4, CU_TENSOR_MAP_SWIZZLE_128B, P256);
    const cuuint64_t dC[5] = {1024, 2, 4, 2, 64}, sC[4] = {2048, 4 * 2048, 2 * 2048, 16 * 2048};
    const cuuint32_t bC[5] = {64, 2, 4, 2, 4};
    CUtensorMap tmCre = make_map(enc, d_in[8], 5, dC, sC, bC, CU_TENSOR_MAP_SWIZZLE_128B, P256);
    CUtensorMap tmCim = make_map(enc, d_in[9], 5, dC, sC, bC, CU_TENSOR_MAP_SWIZZLE_128B, P256);

    const cuuint64_t dU[2] = {8192, 256}, sU[1] = {16384};
    const cuuint32_t bU[2] = {64, 64};
    CUtensorMap tmUst = make_map(enc, pX, 2, dU, sU, bU, CU_TENSOR_MAP_SWIZZLE_128B, P0);
    const cuuint64_t dF[2] = {512 * 1026 / 8, 4}, sF[1] = {512 * 1026};
    const cuuint32_t bF[2] = {WPITCH / 8, 4};
    CUtensorMap tmWr = make_map(enc, d_in[1], 2, dF, sF, bF, CU_TENSOR_MAP_SWIZZLE_NONE, P0, CU_TENSOR_MAP_DATA_TYPE_UINT64);
    CUtensorMap tmWi = make_map(enc, d_in[2], 2, dF, sF, bF, CU_TENSOR_MAP_SWIZZLE_NONE, P0, CU_TENSOR_MAP_DATA_TYPE_UINT64);

    const cuuint64_t dA[3] = {1024, 64, 32}, sA[2] = {32 * 2048, 2048};
    const cuuint32_t bA[3] = {32, 64, 1};
    CUtensorMap tmXa = make_map(enc, d_in[0], 3, dA, sA, bA, CU_TENSOR_MAP_SWIZZLE_64B, XA_PROMO);

    Params p;
    p.wr = (const __nv_bfloat16*)d_in[1];
    p.wi = (const __nv_bfloat16*)d_in[2];
    p.lre = (const __nv_bfloat16*)d_in[4];
    p.lim = (const __nv_bfloat16*)d_in[5];
    p.ldt = (const __nv_bfloat16*)d_in[10];
    p.dsk = (const __nv_bfloat16*)d_in[11];
    p.out = (float*)d_out;
    int dev = 0, sms = 0;
    cudaGetDevice(&dev);
    cudaDeviceGetAttribute(&sms, cudaDevAttrMultiProcessorCount, dev);
    auto kernel = sms == 132 ? fused_kernel<true> : fused_kernel<false>;
    cudaFuncSetAttribute(kernel, cudaFuncAttributeMaxDynamicSharedMemorySize, SMEM_BYTES);
    kernel<<<132, 512, SMEM_BYTES>>>(tmX, tmBre, tmBim, tmCre, tmCim, tmXd, tmUst, tmWr, tmWi, tmXa, p);
}
```

```cpp
#include <cuda_runtime.h>
#include <cuda.h>
#include <cuda_bf16.h>
#include <stdint.h>

#define NST 5
#define WPITCH 1056
#define OFF_P (NST * 32768)
#define OFF_F (OFF_P + 32768)
#define OFF_WD (OFF_F + 8192)
#define OFF_WM (OFF_WD + 8 * WPITCH)
#define OFF_BAR (OFF_F + 32768)
#define OFF_LAM (OFF_BAR + 432)
#define OFF_WSP (OFF_LAM + 2048)
#define OFF_PROF (OFF_WSP + 128)
#define SMEM_BYTES OFF_PROF
#define B_FULL 0
#define B_HL 40
#define B_EP 120
#define B_HR 128
#define B_XD 144
#define B_FG 160
#define B_WSP 168
#define B_WD 176
#define B_DONE 184
#define B_LD 192
#define B_RAW 200
#define B_LAM 208
#define B_IN 216
#define B_XIN 248
#define B_EMPTY 256
#define B_STG 320
#define B_WFREE 328
#define B_HOWN 336
#define B_STGU 368
#define B_P3M 384
#define B_EPOCH 416

#define PACE_U 20
#define PACE_V 20
#define XA_PACE 200
#define XA_PACE2 100
#define XA_TAB 0
#define XA_TABP 200
#define PACE_O 400
#define PACE_ON 2
#define XA_PROMO CU_TENSOR_MAP_L2_PROMOTION_L2_128B
#define TAB_T0 500
#define LAM_T0 1000
#define DEFER 0
#define UHINT 1
#define VPOS 2
#define VPOS0 8
#define GOV_T 100
#define GOV_K0 16
#define GOV_N 22
#define TIDMAP threadIdx.x
#define U1POS 2
#define WPFB B_XIN
#define VS0 16
#define YT 1
#define MPP 2
#define MPY 0
#define XA_N0 2
#define XA_T0 0
#define PACE_X 200
#define SKEW 4
#define SPIN_LIMIT (1u << 15)

__device__ __align__(1024) uint8_t g_X[8 << 20];
__device__ __align__(1024) uint8_t g_H[8 << 20];
__device__ __align__(1024) uint4 g_carry[16 * 512];
__device__ __align__(128) unsigned g_cnt[128];
__device__ __align__(128) unsigned g_epoch[132 * 8];

#define STAMP(i) do { } while (0)
#define STAMPO(i, o) do { } while (0)
#define STAMPW(a, b) do { } while (0)
#define STAMPX(a, b) do { } while (0)
#define STAMP5(i) do { } while (0)
#define STAMP6(i) do { } while (0)
#define STAMP3(i) do { } while (0)

#define TAB_FG 0
#define TAB_G 8192
#define TAB_F1 40960
#define TAB_T 49152
#define TAB_SP 57344
#define TAB_TW1 73728
#define TAB_TW3 75776
#define TAB_PC 83968
__device__ __align__(1024) const uint32_t g_tab[21248] = {
0x80003d80,0x80003d80,0x80003d80,0x80003d80,0x80003d80,0x80003d80,0x80003d80,0x80003d80,0x80003d80,0x80003d80,0x80003d80,0x80003d80,0x80003d80,0x80003d80,0x80003d80,0x80003d80,
0x80003d80,0x80003d80,0x80003d80,0x80003d80,0x80003d80,0x80003d80,0x80003d80,0x80003d80,0x80003d80,0x80003d80,0x80003d80,0x80003d80,0x80003d80,0x80003d80,0x80003d80,0x80003d80,
0x3d353d35,0x3d35bd35,0xbd35bd35,0xbd353d35,0x80003d80,0x3d800000,0x8000bd80,0xbd800000,0x3d353d35,0x3d35bd35,0xbd35bd35,0xbd353d35,0x80003d80,0x3d800000,0x8000bd80,0xbd800000,
0x3d353d35,0x3d35bd35,0xbd35bd35,0xbd353d35,0x80003d80,0x3d800000,0x8000bd80,0xbd800000,0x3d353d35,0x3d35bd35,0xbd35bd35,0xbd353d35,0x80003d80,0x3d800000,0x8000bd80,0xbd800000,
0x3d800000,0x3d6dbcc4,0x3d35bd35,0x3cc4bd6d,0x3d7bbc48,0x3d55bd0e,0x3d0ebd55,0x3c48bd7b,0x80003d80,0x3cc43d6d,0x3d353d35,0x3d6d3cc4,0x3c483d7b,0x3d0e3d55,0x3d553d0e,0x3d7b3c48,
0xbd800000,0xbd6d3cc4,0xbd353d35,0xbcc43d6d,0xbd7b3c48,0xbd553d0e,0xbd0e3d55,0xbc483d7b,0x8000bd80,0xbcc4bd6d,0xbd35bd35,0xbd6dbcc4,0xbc48bd7b,0xbd0ebd55,0xbd55bd0e,0xbd7bbc48,
0x3d0ebd55,0xbd7bbc48,0x3c483d7b,0x3d55bd0e,0x3d800000,0xbcc4bd6d,0xbd353d35,0x3d6d3cc4,0x3d553d0e,0x3c48bd7b,0xbd7b3c48,0x3d0e3d55,0x80003d80,0x3d6dbcc4,0xbd35bd35,0xbcc43d6d,
0xbd0e3d55,0x3d7b3c48,0xbc48bd7b,0xbd553d0e,0xbd800000,0x3cc43d6d,0x3d35bd35,0xbd6dbcc4,0xbd55bd0e,0xbc483d7b,0x3d7bbc48,0xbd0ebd55,0x8000bd80,0xbd6d3cc4,0x3d353d35,0x3cc4bd6d,
0x80003d80,0x3d353d35,0x3d800000,0x3d35bd35,0x3cc43d6d,0x3d6d3cc4,0x3d6dbcc4,0x3cc4bd6d,0x8000bd80,0xbd35bd35,0xbd800000,0xbd353d35,0xbcc4bd6d,0xbd6dbcc4,0xbd6d3cc4,0xbcc43d6d,
0x80003d80,0x3d353d35,0x3d800000,0x3d35bd35,0x3cc43d6d,0x3d6d3cc4,0x3d6dbcc4,0x3cc4bd6d,0x8000bd80,0xbd35bd35,0xbd800000,0xbd353d35,0xbcc4bd6d,0xbd6dbcc4,0xbd6d3cc4,0xbcc43d6d,
0x3d6d3cc4,0xbcc4bd6d,0xbcc43d6d,0x3d6dbcc4,0x80003d80,0x3d35bd35,0xbd800000,0x3d353d35,0xbd6dbcc4,0x3cc43d6d,0x3cc4bd6d,0xbd6d3cc4,0x8000bd80,0xbd353d35,0x3d800000,0xbd35bd35,
0x3d6d3cc4,0xbcc4bd6d,0xbcc43d6d,0x3d6dbcc4,0x80003d80,0x3d35bd35,0xbd800000,0x3d353d35,0xbd6dbcc4,0x3cc43d6d,0x3cc4bd6d,0xbd6d3cc4,0x8000bd80,0xbd353d35,0x3d800000,0xbd35bd35,
0x3d800000,0x3cc4bd6d,0xbd35bd35,0xbd6d3cc4,0x3d55bd0e,0xbc48bd7b,0xbd7bbc48,0xbd0e3d55,0x8000bd80,0xbd6dbcc4,0xbd353d35,0x3cc43d6d,0xbd0ebd55,0xbd7b3c48,0xbc483d7b,0x3d553d0e,
0xbd800000,0xbcc43d6d,0x3d353d35,0x3d6dbcc4,0xbd553d0e,0x3c483d7b,0x3d7b3c48,0x3d0ebd55,0x80003d80,0x3d6d3cc4,0x3d35bd35,0xbcc4bd6d,0x3d0e3d55,0x3d7bbc48,0x3c48bd7b,0xbd55bd0e,
0x3c48bd7b,0xbd0e3d55,0x3d55bd0e,0xbd7b3c48,0x3d800000,0xbd6dbcc4,0x3d353d35,0xbcc4bd6d,0xbd7bbc48,0x3d553d0e,0xbd0ebd55,0x3c483d7b,0x8000bd80,0xbcc43d6d,0x3d35bd35,0xbd6d3cc4,
0xbc483d7b,0x3d0ebd55,0xbd553d0e,0x3d7bbc48,0xbd800000,0x3d6d3cc4,0xbd35bd35,0x3cc43d6d,0x3d7b3c48,0xbd55bd0e,0x3d0e3d55,0xbc48bd7b,0x80003d80,0x3cc4bd6d,0xbd353d35,0x3d6dbcc4,
0x3d800000,0x3d800000,0x3d800000,0x3d800000,0x3d800000,0x3d800000,0x3d800000,0x3d800000,0x3d800000,0x3d800000,0x3d800000,0x3d800000,0x3d800000,0x3d800000,0x3d800000,0x3d800000,
0x3d800000,0x3d800000,0x3d800000,0x3d800000,0x3d800000,0x3d800000,0x3d800000,0x3d800000,0x3d800000,0x3d800000,0x3d800000,0x3d800000,0x3d800000,0x3d800000,0x3d800000,0x3d800000,
0x3d35bd35,0xbd35bd35,0xbd353d35,0x3d353d35,0x3d800000,0xbd80,0xbd800000,0x3d80,0x3d35bd35,0xbd35bd35,0xbd353d35,0x3d353d35,0x3d800000,0xbd80,0xbd800000,0x3d80,
0x3d35bd35,0xbd35bd35,0xbd353d35,0x3d353d35,0x3d800000,0xbd80,0xbd800000,0x3d80,0x3d35bd35,0xbd35bd35,0xbd353d35,0x3d353d35,0x3d800000,0xbd80,0xbd800000,0x3d80,
0xbd80,0xbcc4bd6d,0xbd35bd35,0xbd6dbcc4,0xbc48bd7b,0xbd0ebd55,0xbd55bd0e,0xbd7bbc48,0x3d800000,0x3d6dbcc4,0x3d35bd35,0x3cc4bd6d,0x3d7bbc48,0x3d55bd0e,0x3d0ebd55,0x3c48bd7b,
0x3d80,0x3cc43d6d,0x3d353d35,0x3d6d3cc4,0x3c483d7b,0x3d0e3d55,0x3d553d0e,0x3d7b3c48,0xbd800000,0xbd6d3cc4,0xbd353d35,0xbcc43d6d,0xbd7b3c48,0xbd553d0e,0xbd0e3d55,0xbc483d7b,
0xbd55bd0e,0xbc483d7b,0x3d7bbc48,0xbd0ebd55,0xbd80,0xbd6d3cc4,0x3d353d35,0x3cc4bd6d,0x3d0ebd55,0xbd7bbc48,0x3c483d7b,0x3d55bd0e,0x3d800000,0xbcc4bd6d,0xbd353d35,0x3d6d3cc4,
0x3d553d0e,0x3c48bd7b,0xbd7b3c48,0x3d0e3d55,0x3d80,0x3d6dbcc4,0xbd35bd35,0xbcc43d6d,0xbd0e3d55,0x3d7b3c48,0xbc48bd7b,0xbd553d0e,0xbd800000,0x3cc43d6d,0x3d35bd35,0xbd6dbcc4,
0x3d800000,0x3d35bd35,0xbd80,0xbd35bd35,0x3d6dbcc4,0x3cc4bd6d,0xbcc4bd6d,0xbd6dbcc4,0xbd800000,0xbd353d35,0x3d80,0x3d353d35,0xbd6d3cc4,0xbcc43d6d,0x3cc43d6d,0x3d6d3cc4,
0x3d800000,0x3d35bd35,0xbd80,0xbd35bd35,0x3d6dbcc4,0x3cc4bd6d,0xbcc4bd6d,0xbd6dbcc4,0xbd800000,0xbd353d35,0x3d80,0x3d353d35,0xbd6d3cc4,0xbcc43d6d,0x3cc43d6d,0x3d6d3cc4,
0x3cc4bd6d,0xbd6d3cc4,0x3d6d3cc4,0xbcc4bd6d,0x3d800000,0xbd35bd35,0x3d80,0x3d35bd35,0xbcc43d6d,0x3d6dbcc4,0xbd6dbcc4,0x3cc43d6d,0xbd800000,0x3d353d35,0xbd80,0xbd353d35,
0x3cc4bd6d,0xbd6d3cc4,0x3d6d3cc4,0xbcc4bd6d,0x3d800000,0xbd35bd35,0x3d80,0x3d35bd35,0xbcc43d6d,0x3d6dbcc4,0xbd6dbcc4,0x3cc43d6d,0xbd800000,0x3d353d35,0xbd80,0xbd353d35,
0xbd80,0xbd6dbcc4,0xbd353d35,0x3cc43d6d,0xbd0ebd55,0xbd7b3c48,0xbc483d7b,0x3d553d0e,0xbd800000,0xbcc43d6d,0x3d353d35,0x3d6dbcc4,0xbd553d0e,0x3c483d7b,0x3d7b3c48,0x3d0ebd55,
0x3d80,0x3d6d3cc4,0x3d35bd35,0xbcc4bd6d,0x3d0e3d55,0x3d7bbc48,0x3c48bd7b,0xbd55bd0e,0x3d800000,0x3cc4bd6d,0xbd35bd35,0xbd6d3cc4,0x3d55bd0e,0xbc48bd7b,0xbd7bbc48,0xbd0e3d55,
0xbd7bbc48,0x3d553d0e,0xbd0ebd55,0x3c483d7b,0xbd80,0xbcc43d6d,0x3d35bd35,0xbd6d3cc4,0xbc483d7b,0x3d0ebd55,0xbd553d0e,0x3d7bbc48,0xbd800000,0x3d6d3cc4,0xbd35bd35,0x3cc43d6d,
0x3d7b3c48,0xbd55bd0e,0x3d0e3d55,0xbc48bd7b,0x3d80,0x3cc4bd6d,0xbd353d35,0x3d6dbcc4,0x3c48bd7b,0xbd0e3d55,0x3d55bd0e,0xbd7b3c48,0x3d800000,0xbd6dbcc4,0x3d353d35,0xbcc4bd6d,
0x80003d80,0x8000bd80,0x80003d80,0x8000bd80,0x3d800000,0xbd800000,0x3d800000,0xbd800000,0x80003d80,0x8000bd80,0x80003d80,0x8000bd80,0x3d800000,0xbd800000,0x3d800000,0xbd800000,
0x80003d80,0x8000bd80,0x80003d80,0x8000bd80,0x3d800000,0xbd800000,0x3d800000,0xbd800000,0x80003d80,0x8000bd80,0x80003d80,0x8000bd80,0x3d800000,0xbd800000,0x3d800000,0xbd800000,
0x3d35bd35,0x3d353d35,0xbd353d35,0xbd35bd35,0x80003d80,0xbd800000,0x8000bd80,0x3d800000,0x3d35bd35,0x3d353d35,0xbd353d35,0xbd35bd35,0x80003d80,0xbd800000,0x8000bd80,0x3d800000,
0x3d35bd35,0x3d353d35,0xbd353d35,0xbd35bd35,0x80003d80,0xbd800000,0x8000bd80,0x3d800000,0x3d35bd35,0x3d353d35,0xbd353d35,0xbd35bd35,0x80003d80,0xbd800000,0x8000bd80,0x3d800000,
0x3d800000,0xbd6d3cc4,0x3d35bd35,0xbcc43d6d,0xbc48bd7b,0x3d0e3d55,0xbd55bd0e,0x3d7b3c48,0x80003d80,0xbcc4bd6d,0x3d353d35,0xbd6dbcc4,0x3d7bbc48,0xbd553d0e,0x3d0ebd55,0xbc483d7b,
0xbd800000,0x3d6dbcc4,0xbd353d35,0x3cc4bd6d,0x3c483d7b,0xbd0ebd55,0x3d553d0e,0xbd7bbc48,0x8000bd80,0x3cc43d6d,0xbd35bd35,0x3d6d3cc4,0xbd7b3c48,0x3d55bd0e,0xbd0e3d55,0x3c48bd7b,
0xbd55bd0e,0x3c48bd7b,0x3d7bbc48,0x3d0e3d55,0x3d800000,0x3cc43d6d,0xbd353d35,0xbd6dbcc4,0x3d0ebd55,0x3d7b3c48,0x3c483d7b,0xbd553d0e,0x80003d80,0xbd6d3cc4,0xbd35bd35,0x3cc4bd6d,
0x3d553d0e,0xbc483d7b,0xbd7b3c48,0xbd0ebd55,0xbd800000,0xbcc4bd6d,0x3d35bd35,0x3d6d3cc4,0xbd0e3d55,0xbd7bbc48,0xbc48bd7b,0x3d55bd0e,0x8000bd80,0x3d6dbcc4,0x3d353d35,0xbcc43d6d,
0x80003d80,0xbd35bd35,0x3d800000,0xbd353d35,0x3d6dbcc4,0xbcc43d6d,0xbcc4bd6d,0x3d6d3cc4,0x8000bd80,0x3d353d35,0xbd800000,0x3d35bd35,0xbd6d3cc4,0x3cc4bd6d,0x3cc43d6d,0xbd6dbcc4,
0x80003d80,0xbd35bd35,0x3d800000,0xbd353d35,0x3d6dbcc4,0xbcc43d6d,0xbcc4bd6d,0x3d6d3cc4,0x8000bd80,0x3d353d35,0xbd800000,0x3d35bd35,0xbd6d3cc4,0x3cc4bd6d,0x3cc43d6d,0xbd6dbcc4,
0x3cc4bd6d,0x3d6dbcc4,0x3d6d3cc4,0x3cc43d6d,0x80003d80,0xbd353d35,0xbd800000,0xbd35bd35,0xbcc43d6d,0xbd6d3cc4,0xbd6dbcc4,0xbcc4bd6d,0x8000bd80,0x3d35bd35,0x3d800000,0x3d353d35,
0x3cc4bd6d,0x3d6dbcc4,0x3d6d3cc4,0x3cc43d6d,0x80003d80,0xbd353d35,0xbd800000,0xbd35bd35,0xbcc43d6d,0xbd6d3cc4,0xbd6dbcc4,0xbcc4bd6d,0x8000bd80,0x3d35bd35,0x3d800000,0x3d353d35,
0x3d800000,0xbcc43d6d,0xbd35bd35,0x3d6dbcc4,0xbd0ebd55,0x3d7bbc48,0xbc483d7b,0xbd55bd0e,0x8000bd80,0x3d6d3cc4,0xbd353d35,0xbcc4bd6d,0xbd553d0e,0xbc48bd7b,0x3d7b3c48,0xbd0e3d55,
0xbd800000,0x3cc4bd6d,0x3d353d35,0xbd6d3cc4,0x3d0e3d55,0xbd7b3c48,0x3c48bd7b,0x3d553d0e,0x80003d80,0xbd6dbcc4,0x3d35bd35,0x3cc43d6d,0x3d55bd0e,0x3c483d7b,0xbd7bbc48,0x3d0ebd55,
0xbd7bbc48,0xbd55bd0e,0xbd0ebd55,0xbc48bd7b,0x3d800000,0x3d6d3cc4,0x3d353d35,0x3cc43d6d,0xbc483d7b,0xbd0e3d55,0xbd553d0e,0xbd7b3c48,0x8000bd80,0x3cc4bd6d,0x3d35bd35,0x3d6dbcc4,
0x3d7b3c48,0x3d553d0e,0x3d0e3d55,0x3c483d7b,0xbd800000,0xbd6dbcc4,0xbd35bd35,0xbcc4bd6d,0x3c48bd7b,0x3d0ebd55,0x3d55bd0e,0x3d7bbc48,0x80003d80,0xbcc43d6d,0xbd353d35,0xbd6d3cc4,
0x3d800000,0xbd800000,0x3d800000,0xbd800000,0xbd80,0x3d80,0xbd80,0x3d80,0x3d800000,0xbd800000,0x3d800000,0xbd800000,0xbd80,0x3d80,0xbd80,0x3d80,
0x3d800000,0xbd800000,0x3d800000,0xbd800000,0xbd80,0x3d80,0xbd80,0x3d80,0x3d800000,0xbd800000,0x3d800000,0xbd800000,0xbd80,0x3d80,0xbd80,0x3d80,
0xbd35bd35,0x3d35bd35,0x3d353d35,0xbd353d35,0x3d800000,0x3d80,0xbd800000,0xbd80,0xbd35bd35,0x3d35bd35,0x3d353d35,0xbd353d35,0x3d800000,0x3d80,0xbd800000,0xbd80,
0xbd35bd35,0x3d35bd35,0x3d353d35,0xbd353d35,0x3d800000,0x3d80,0xbd800000,0xbd80,0xbd35bd35,0x3d35bd35,0x3d353d35,0xbd353d35,0x3d800000,0x3d80,0xbd800000,0xbd80,
0xbd80,0x3cc43d6d,0xbd35bd35,0x3d6d3cc4,0xbd7b3c48,0x3d55bd0e,0xbd0e3d55,0x3c48bd7b,0x3d800000,0xbd6d3cc4,0x3d35bd35,0xbcc43d6d,0xbc48bd7b,0x3d0e3d55,0xbd55bd0e,0x3d7b3c48,
0x3d80,0xbcc4bd6d,0x3d353d35,0xbd6dbcc4,0x3d7bbc48,0xbd553d0e,0x3d0ebd55,0xbc483d7b,0xbd800000,0x3d6dbcc4,0xbd353d35,0x3cc4bd6d,0x3c483d7b,0xbd0ebd55,0x3d553d0e,0xbd7bbc48,
0xbd0e3d55,0xbd7bbc48,0xbc48bd7b,0x3d55bd0e,0xbd80,0x3d6dbcc4,0x3d353d35,0xbcc43d6d,0xbd55bd0e,0x3c48bd7b,0x3d7bbc48,0x3d0e3d55,0x3d800000,0x3cc43d6d,0xbd353d35,0xbd6dbcc4,
0x3d0ebd55,0x3d7b3c48,0x3c483d7b,0xbd553d0e,0x3d80,0xbd6d3cc4,0xbd35bd35,0x3cc4bd6d,0x3d553d0e,0xbc483d7b,0xbd7b3c48,0xbd0ebd55,0xbd800000,0xbcc4bd6d,0x3d35bd35,0x3d6d3cc4,
0x3d800000,0xbd353d35,0xbd80,0x3d353d35,0xbcc4bd6d,0x3d6d3cc4,0xbd6d3cc4,0x3cc4bd6d,0xbd800000,0x3d35bd35,0x3d80,0xbd35bd35,0x3cc43d6d,0xbd6dbcc4,0x3d6dbcc4,0xbcc43d6d,
0x3d800000,0xbd353d35,0xbd80,0x3d353d35,0xbcc4bd6d,0x3d6d3cc4,0xbd6d3cc4,0x3cc4bd6d,0xbd800000,0x3d35bd35,0x3d80,0xbd35bd35,0x3cc43d6d,0xbd6dbcc4,0x3d6dbcc4,0xbcc43d6d,
0xbd6dbcc4,0xbcc4bd6d,0x3cc4bd6d,0x3d6dbcc4,0x3d800000,0x3d353d35,0x3d80,0xbd353d35,0x3d6d3cc4,0x3cc43d6d,0xbcc43d6d,0xbd6d3cc4,0xbd800000,0xbd35bd35,0xbd80,0x3d35bd35,
0xbd6dbcc4,0xbcc4bd6d,0x3cc4bd6d,0x3d6dbcc4,0x3d800000,0x3d353d35,0x3d80,0xbd353d35,0x3d6d3cc4,0x3cc43d6d,0xbcc43d6d,0xbd6d3cc4,0xbd800000,0xbd35bd35,0xbd80,0x3d35bd35,
0xbd80,0x3d6d3cc4,0xbd353d35,0xbcc4bd6d,0xbd553d0e,0xbc48bd7b,0x3d7b3c48,0xbd0e3d55,0xbd800000,0x3cc4bd6d,0x3d353d35,0xbd6d3cc4,0x3d0e3d55,0xbd7b3c48,0x3c48bd7b,0x3d553d0e,
0x3d80,0xbd6dbcc4,0x3d35bd35,0x3cc43d6d,0x3d55bd0e,0x3c483d7b,0xbd7bbc48,0x3d0ebd55,0x3d800000,0xbcc43d6d,0xbd35bd35,0x3d6dbcc4,0xbd0ebd55,0x3d7bbc48,0xbc483d7b,0xbd55bd0e,
0xbc483d7b,0xbd0e3d55,0xbd553d0e,0xbd7b3c48,0xbd80,0x3cc4bd6d,0x3d35bd35,0x3d6dbcc4,0x3d7b3c48,0x3d553d0e,0x3d0e3d55,0x3c483d7b,0xbd800000,0xbd6dbcc4,0xbd35bd35,0xbcc4bd6d,
0x3c48bd7b,0x3d0ebd55,0x3d55bd0e,0x3d7bbc48,0x3d80,0xbcc43d6d,0xbd353d35,0xbd6d3cc4,0xbd7bbc48,0xbd55bd0e,0xbd0ebd55,0xbc48bd7b,0x3d800000,0x3d6d3cc4,0x3d353d35,0x3cc43d6d,
0x80003d80,0x80003d80,0x80003d80,0x80003d80,0x8000bd80,0x8000bd80,0x8000bd80,0x8000bd80,0x80003d80,0x80003d80,0x80003d80,0x80003d80,0x8000bd80,0x8000bd80,0x8000bd80,0x8000bd80,
0x80003d80,0x80003d80,0x80003d80,0x80003d80,0x8000bd80,0x8000bd80,0x8000bd80,0x8000bd80,0x80003d80,0x80003d80,0x80003d80,0x80003d80,0x8000bd80,0x8000bd80,0x8000bd80,0x8000bd80,
0xbd35bd35,0xbd353d35,0x3d353d35,0x3d35bd35,0x80003d80,0x3d800000,0x8000bd80,0xbd800000,0xbd35bd35,0xbd353d35,0x3d353d35,0x3d35bd35,0x80003d80,0x3d800000,0x8000bd80,0xbd800000,
0xbd35bd35,0xbd353d35,0x3d353d35,0x3d35bd35,0x80003d80,0x3d800000,0x8000bd80,0xbd800000,0xbd35bd35,0xbd353d35,0x3d353d35,0x3d35bd35,0x80003d80,0x3d800000,0x8000bd80,0xbd800000,
0x3d800000,0x3d6dbcc4,0x3d35bd35,0x3cc4bd6d,0xbd7b3c48,0xbd553d0e,0xbd0e3d55,0xbc483d7b,0x80003d80,0x3cc43d6d,0x3d353d35,0x3d6d3cc4,0xbc48bd7b,0xbd0ebd55,0xbd55bd0e,0xbd7bbc48,
0xbd800000,0xbd6d3cc4,0xbd353d35,0xbcc43d6d,0x3d7bbc48,0x3d55bd0e,0x3d0ebd55,0x3c48bd7b,0x8000bd80,0xbcc4bd6d,0xbd35bd35,0xbd6dbcc4,0x3c483d7b,0x3d0e3d55,0x3d553d0e,0x3d7b3c48,
0xbd0e3d55,0x3d7b3c48,0xbc48bd7b,0xbd553d0e,0x3d800000,0xbcc4bd6d,0xbd353d35,0x3d6d3cc4,0xbd55bd0e,0xbc483d7b,0x3d7bbc48,0xbd0ebd55,0x80003d80,0x3d6dbcc4,0xbd35bd35,0xbcc43d6d,
0x3d0ebd55,0xbd7bbc48,0x3c483d7b,0x3d55bd0e,0xbd800000,0x3cc43d6d,0x3d35bd35,0xbd6dbcc4,0x3d553d0e,0x3c48bd7b,0xbd7b3c48,0x3d0e3d55,0x8000bd80,0xbd6d3cc4,0x3d353d35,0x3cc4bd6d,
0x80003d80,0x3d353d35,0x3d800000,0x3d35bd35,0xbcc4bd6d,0xbd6dbcc4,0xbd6d3cc4,0xbcc43d6d,0x8000bd80,0xbd35bd35,0xbd800000,0xbd353d35,0x3cc43d6d,0x3d6d3cc4,0x3d6dbcc4,0x3cc4bd6d,
0x80003d80,0x3d353d35,0x3d800000,0x3d35bd35,0xbcc4bd6d,0xbd6dbcc4,0xbd6d3cc4,0xbcc43d6d,0x8000bd80,0xbd35bd35,0xbd800000,0xbd353d35,0x3cc43d6d,0x3d6d3cc4,0x3d6dbcc4,0x3cc4bd6d,
0xbd6dbcc4,0x3cc43d6d,0x3cc4bd6d,0xbd6d3cc4,0x80003d80,0x3d35bd35,0xbd800000,0x3d353d35,0x3d6d3cc4,0xbcc4bd6d,0xbcc43d6d,0x3d6dbcc4,0x8000bd80,0xbd353d35,0x3d800000,0xbd35bd35,
0xbd6dbcc4,0x3cc43d6d,0x3cc4bd6d,0xbd6d3cc4,0x80003d80,0x3d35bd35,0xbd800000,0x3d353d35,0x3d6d3cc4,0xbcc4bd6d,0xbcc43d6d,0x3d6dbcc4,0x8000bd80,0xbd353d35,0x3d800000,0xbd35bd35,
0x3d800000,0x3cc4bd6d,0xbd35bd35,0xbd6d3cc4,0xbd553d0e,0x3c483d7b,0x3d7b3c48,0x3d0ebd55,0x8000bd80,0xbd6dbcc4,0xbd353d35,0x3cc43d6d,0x3d0e3d55,0x3d7bbc48,0x3c48bd7b,0xbd55bd0e,
0xbd800000,0xbcc43d6d,0x3d353d35,0x3d6dbcc4,0x3d55bd0e,0xbc48bd7b,0xbd7bbc48,0xbd0e3d55,0x80003d80,0x3d6d3cc4,0x3d35bd35,0xbcc4bd6d,0xbd0ebd55,0xbd7b3c48,0xbc483d7b,0x3d553d0e,
0xbc483d7b,0x3d0ebd55,0xbd553d0e,0x3d7bbc48,0x3d800000,0xbd6dbcc4,0x3d353d35,0xbcc4bd6d,0x3d7b3c48,0xbd55bd0e,0x3d0e3d55,0xbc48bd7b,0x8000bd80,0xbcc43d6d,0x3d35bd35,0xbd6d3cc4,
0x3c48bd7b,0xbd0e3d55,0x3d55bd0e,0xbd7b3c48,0xbd800000,0x3d6d3cc4,0xbd35bd35,0x3cc43d6d,0xbd7bbc48,0x3d553d0e,0xbd0ebd55,0x3c483d7b,0x80003d80,0x3cc4bd6d,0xbd353d35,0x3d6dbcc4,
0x3d800000,0x3d800000,0x3d800000,0x3d800000,0xbd800000,0xbd800000,0xbd800000,0xbd800000,0x3d800000,0x3d800000,0x3d800000,0x3d800000,0xbd800000,0xbd800000,0xbd800000,0xbd800000,
0x3d800000,0x3d800000,0x3d800000,0x3d800000,0xbd800000,0xbd800000,0xbd800000,0xbd800000,0x3d800000,0x3d800000,0x3d800000,0x3d800000,0xbd800000,0xbd800000,0xbd800000,0xbd800000,
0xbd353d35,0x3d353d35,0x3d35bd35,0xbd35bd35,0x3d800000,0xbd80,0xbd800000,0x3d80,0xbd353d35,0x3d353d35,0x3d35bd35,0xbd35bd35,0x3d800000,0xbd80,0xbd800000,0x3d80,
0xbd353d35,0x3d353d35,0x3d35bd35,0xbd35bd35,0x3d800000,0xbd80,0xbd800000,0x3d80,0xbd353d35,0x3d353d35,0x3d35bd35,0xbd35bd35,0x3d800000,0xbd80,0xbd800000,0x3d80,
0xbd80,0xbcc4bd6d,0xbd35bd35,0xbd6dbcc4,0x3c483d7b,0x3d0e3d55,0x3d553d0e,0x3d7b3c48,0x3d800000,0x3d6dbcc4,0x3d35bd35,0x3cc4bd6d,0xbd7b3c48,0xbd553d0e,0xbd0e3d55,0xbc483d7b,
0x3d80,0x3cc43d6d,0x3d353d35,0x3d6d3cc4,0xbc48bd7b,0xbd0ebd55,0xbd55bd0e,0xbd7bbc48,0xbd800000,0xbd6d3cc4,0xbd353d35,0xbcc43d6d,0x3d7bbc48,0x3d55bd0e,0x3d0ebd55,0x3c48bd7b,
0x3d553d0e,0x3c48bd7b,0xbd7b3c48,0x3d0e3d55,0xbd80,0xbd6d3cc4,0x3d353d35,0x3cc4bd6d,0xbd0e3d55,0x3d7b3c48,0xbc48bd7b,0xbd553d0e,0x3d800000,0xbcc4bd6d,0xbd353d35,0x3d6d3cc4,
0xbd55bd0e,0xbc483d7b,0x3d7bbc48,0xbd0ebd55,0x3d80,0x3d6dbcc4,0xbd35bd35,0xbcc43d6d,0x3d0ebd55,0xbd7bbc48,0x3c483d7b,0x3d55bd0e,0xbd800000,0x3cc43d6d,0x3d35bd35,0xbd6dbcc4,
0x3d800000,0x3d35bd35,0xbd80,0xbd35bd35,0xbd6d3cc4,0xbcc43d6d,0x3cc43d6d,0x3d6d3cc4,0xbd800000,0xbd353d35,0x3d80,0x3d353d35,0x3d6dbcc4,0x3cc4bd6d,0xbcc4bd6d,0xbd6dbcc4,
0x3d800000,0x3d35bd35,0xbd80,0xbd35bd35,0xbd6d3cc4,0xbcc43d6d,0x3cc43d6d,0x3d6d3cc4,0xbd800000,0xbd353d35,0x3d80,0x3d353d35,0x3d6dbcc4,0x3cc4bd6d,0xbcc4bd6d,0xbd6dbcc4,
0xbcc43d6d,0x3d6dbcc4,0xbd6dbcc4,0x3cc43d6d,0x3d800000,0xbd35bd35,0x3d80,0x3d35bd35,0x3cc4bd6d,0xbd6d3cc4,0x3d6d3cc4,0xbcc4bd6d,0xbd800000,0x3d353d35,0xbd80,0xbd353d35,
0xbcc43d6d,0x3d6dbcc4,0xbd6dbcc4,0x3cc43d6d,0x3d800000,0xbd35bd35,0x3d80,0x3d35bd35,0x3cc4bd6d,0xbd6d3cc4,0x3d6d3cc4,0xbcc4bd6d,0xbd800000,0x3d353d35,0xbd80,0xbd353d35,
0xbd80,0xbd6dbcc4,0xbd353d35,0x3cc43d6d,0x3d0e3d55,0x3d7bbc48,0x3c48bd7b,0xbd55bd0e,0xbd800000,0xbcc43d6d,0x3d353d35,0x3d6dbcc4,0x3d55bd0e,0xbc48bd7b,0xbd7bbc48,0xbd0e3d55,
0x3d80,0x3d6d3cc4,0x3d35bd35,0xbcc4bd6d,0xbd0ebd55,0xbd7b3c48,0xbc483d7b,0x3d553d0e,0x3d800000,0x3cc4bd6d,0xbd35bd35,0xbd6d3cc4,0xbd553d0e,0x3c483d7b,0x3d7b3c48,0x3d0ebd55,
0x3d7b3c48,0xbd55bd0e,0x3d0e3d55,0xbc48bd7b,0xbd80,0xbcc43d6d,0x3d35bd35,0xbd6d3cc4,0x3c48bd7b,0xbd0e3d55,0x3d55bd0e,0xbd7b3c48,0xbd800000,0x3d6d3cc4,0xbd35bd35,0x3cc43d6d,
0xbd7bbc48,0x3d553d0e,0xbd0ebd55,0x3c483d7b,0x3d80,0x3cc4bd6d,0xbd353d35,0x3d6dbcc4,0xbc483d7b,0x3d0ebd55,0xbd553d0e,0x3d7bbc48,0x3d800000,0xbd6dbcc4,0x3d353d35,0xbcc4bd6d,
0x80003d80,0x8000bd80,0x80003d80,0x8000bd80,0xbd800000,0x3d800000,0xbd800000,0x3d800000,0x80003d80,0x8000bd80,0x80003d80,0x8000bd80,0xbd800000,0x3d800000,0xbd800000,0x3d800000,
0x80003d80,0x8000bd80,0x80003d80,0x8000bd80,0xbd800000,0x3d800000,0xbd800000,0x3d800000,0x80003d80,0x8000bd80,0x80003d80,0x8000bd80,0xbd800000,0x3d800000,0xbd800000,0x3d800000,
0xbd353d35,0xbd35bd35,0x3d35bd35,0x3d353d35,0x80003d80,0xbd800000,0x8000bd80,0x3d800000,0xbd353d35,0xbd35bd35,0x3d35bd35,0x3d353d35,0x80003d80,0xbd800000,0x8000bd80,0x3d800000,
0xbd353d35,0xbd35bd35,0x3d35bd35,0x3d353d35,0x80003d80,0xbd800000,0x8000bd80,0x3d800000,0xbd353d35,0xbd35bd35,0x3d35bd35,0x3d353d35,0x80003d80,0xbd800000,0x8000bd80,0x3d800000,
0x3d800000,0xbd6d3cc4,0x3d35bd35,0xbcc43d6d,0x3c483d7b,0xbd0ebd55,0x3d553d0e,0xbd7bbc48,0x80003d80,0xbcc4bd6d,0x3d353d35,0xbd6dbcc4,0xbd7b3c48,0x3d55bd0e,0xbd0e3d55,0x3c48bd7b,
0xbd800000,0x3d6dbcc4,0xbd353d35,0x3cc4bd6d,0xbc48bd7b,0x3d0e3d55,0xbd55bd0e,0x3d7b3c48,0x8000bd80,0x3cc43d6d,0xbd35bd35,0x3d6d3cc4,0x3d7bbc48,0xbd553d0e,0x3d0ebd55,0xbc483d7b,
0x3d553d0e,0xbc483d7b,0xbd7b3c48,0xbd0ebd55,0x3d800000,0x3cc43d6d,0xbd353d35,0xbd6dbcc4,0xbd0e3d55,0xbd7bbc48,0xbc48bd7b,0x3d55bd0e,0x80003d80,0xbd6d3cc4,0xbd35bd35,0x3cc4bd6d,
0xbd55bd0e,0x3c48bd7b,0x3d7bbc48,0x3d0e3d55,0xbd800000,0xbcc4bd6d,0x3d35bd35,0x3d6d3cc4,0x3d0ebd55,0x3d7b3c48,0x3c483d7b,0xbd553d0e,0x8000bd80,0x3d6dbcc4,0x3d353d35,0xbcc43d6d,
0x80003d80,0xbd35bd35,0x3d800000,0xbd353d35,0xbd6d3cc4,0x3cc4bd6d,0x3cc43d6d,0xbd6dbcc4,0x8000bd80,0x3d353d35,0xbd800000,0x3d35bd35,0x3d6dbcc4,0xbcc43d6d,0xbcc4bd6d,0x3d6d3cc4,
0x80003d80,0xbd35bd35,0x3d800000,0xbd353d35,0xbd6d3cc4,0x3cc4bd6d,0x3cc43d6d,0xbd6dbcc4,0x8000bd80,0x3d353d35,0xbd800000,0x3d35bd35,0x3d6dbcc4,0xbcc43d6d,0xbcc4bd6d,0x3d6d3cc4,
0xbcc43d6d,0xbd6d3cc4,0xbd6dbcc4,0xbcc4bd6d,0x80003d80,0xbd353d35,0xbd800000,0xbd35bd35,0x3cc4bd6d,0x3d6dbcc4,0x3d6d3cc4,0x3cc43d6d,0x8000bd80,0x3d35bd35,0x3d800000,0x3d353d35,
0xbcc43d6d,0xbd6d3cc4,0xbd6dbcc4,0xbcc4bd6d,0x80003d80,0xbd353d35,0xbd800000,0xbd35bd35,0x3cc4bd6d,0x3d6dbcc4,0x3d6d3cc4,0x3cc43d6d,0x8000bd80,0x3d35bd35,0x3d800000,0x3d353d35,
0x3d800000,0xbcc43d6d,0xbd35bd35,0x3d6dbcc4,0x3d0e3d55,0xbd7b3c48,0x3c48bd7b,0x3d553d0e,0x8000bd80,0x3d6d3cc4,0xbd353d35,0xbcc4bd6d,0x3d55bd0e,0x3c483d7b,0xbd7bbc48,0x3d0ebd55,
0xbd800000,0x3cc4bd6d,0x3d353d35,0xbd6d3cc4,0xbd0ebd55,0x3d7bbc48,0xbc483d7b,0xbd55bd0e,0x80003d80,0xbd6dbcc4,0x3d35bd35,0x3cc43d6d,0xbd553d0e,0xbc48bd7b,0x3d7b3c48,0xbd0e3d55,
0x3d7b3c48,0x3d553d0e,0x3d0e3d55,0x3c483d7b,0x3d800000,0x3d6d3cc4,0x3d353d35,0x3cc43d6d,0x3c48bd7b,0x3d0ebd55,0x3d55bd0e,0x3d7bbc48,0x8000bd80,0x3cc4bd6d,0x3d35bd35,0x3d6dbcc4,
0xbd7bbc48,0xbd55bd0e,0xbd0ebd55,0xbc48bd7b,0xbd800000,0xbd6dbcc4,0xbd35bd35,0xbcc4bd6d,0xbc483d7b,0xbd0e3d55,0xbd553d0e,0xbd7b3c48,0x80003d80,0xbcc43d6d,0xbd353d35,0xbd6d3cc4,
0x3d800000,0xbd800000,0x3d800000,0xbd800000,0x3d80,0xbd80,0x3d80,0xbd80,0x3d800000,0xbd800000,0x3d800000,0xbd800000,0x3d80,0xbd80,0x3d80,0xbd80,
0x3d800000,0xbd800000,0x3d800000,0xbd800000,0x3d80,0xbd80,0x3d80,0xbd80,0x3d800000,0xbd800000,0x3d800000,0xbd800000,0x3d80,0xbd80,0x3d80,0xbd80,
0x3d353d35,0xbd353d35,0xbd35bd35,0x3d35bd35,0x3d800000,0x3d80,0xbd800000,0xbd80,0x3d353d35,0xbd353d35,0xbd35bd35,0x3d35bd35,0x3d800000,0x3d80,0xbd800000,0xbd80,
0x3d353d35,0xbd353d35,0xbd35bd35,0x3d35bd35,0x3d800000,0x3d80,0xbd800000,0xbd80,0x3d353d35,0xbd353d35,0xbd35bd35,0x3d35bd35,0x3d800000,0x3d80,0xbd800000,0xbd80,
0xbd80,0x3cc43d6d,0xbd35bd35,0x3d6d3cc4,0x3d7bbc48,0xbd553d0e,0x3d0ebd55,0xbc483d7b,0x3d800000,0xbd6d3cc4,0x3d35bd35,0xbcc43d6d,0x3c483d7b,0xbd0ebd55,0x3d553d0e,0xbd7bbc48,
0x3d80,0xbcc4bd6d,0x3d353d35,0xbd6dbcc4,0xbd7b3c48,0x3d55bd0e,0xbd0e3d55,0x3c48bd7b,0xbd800000,0x3d6dbcc4,0xbd353d35,0x3cc4bd6d,0xbc48bd7b,0x3d0e3d55,0xbd55bd0e,0x3d7b3c48,
0x3d0ebd55,0x3d7b3c48,0x3c483d7b,0xbd553d0e,0xbd80,0x3d6dbcc4,0x3d353d35,0xbcc43d6d,0x3d553d0e,0xbc483d7b,0xbd7b3c48,0xbd0ebd55,0x3d800000,0x3cc43d6d,0xbd353d35,0xbd6dbcc4,
0xbd0e3d55,0xbd7bbc48,0xbc48bd7b,0x3d55bd0e,0x3d80,0xbd6d3cc4,0xbd35bd35,0x3cc4bd6d,0xbd55bd0e,0x3c48bd7b,0x3d7bbc48,0x3d0e3d55,0xbd800000,0xbcc4bd6d,0x3d35bd35,0x3d6d3cc4,
0x3d800000,0xbd353d35,0xbd80,0x3d353d35,0x3cc43d6d,0xbd6dbcc4,0x3d6dbcc4,0xbcc43d6d,0xbd800000,0x3d35bd35,0x3d80,0xbd35bd35,0xbcc4bd6d,0x3d6d3cc4,0xbd6d3cc4,0x3cc4bd6d,
0x3d800000,0xbd353d35,0xbd80,0x3d353d35,0x3cc43d6d,0xbd6dbcc4,0x3d6dbcc4,0xbcc43d6d,0xbd800000,0x3d35bd35,0x3d80,0xbd35bd35,0xbcc4bd6d,0x3d6d3cc4,0xbd6d3cc4,0x3cc4bd6d,
0x3d6d3cc4,0x3cc43d6d,0xbcc43d6d,0xbd6d3cc4,0x3d800000,0x3d353d35,0x3d80,0xbd353d35,0xbd6dbcc4,0xbcc4bd6d,0x3cc4bd6d,0x3d6dbcc4,0xbd800000,0xbd35bd35,0xbd80,0x3d35bd35,
0x3d6d3cc4,0x3cc43d6d,0xbcc43d6d,0xbd6d3cc4,0x3d800000,0x3d353d35,0x3d80,0xbd353d35,0xbd6dbcc4,0xbcc4bd6d,0x3cc4bd6d,0x3d6dbcc4,0xbd800000,0xbd35bd35,0xbd80,0x3d35bd35,
0xbd80,0x3d6d3cc4,0xbd353d35,0xbcc4bd6d,0x3d55bd0e,0x3c483d7b,0xbd7bbc48,0x3d0ebd55,0xbd800000,0x3cc4bd6d,0x3d353d35,0xbd6d3cc4,0xbd0ebd55,0x3d7bbc48,0xbc483d7b,0xbd55bd0e,
0x3d80,0xbd6dbcc4,0x3d35bd35,0x3cc43d6d,0xbd553d0e,0xbc48bd7b,0x3d7b3c48,0xbd0e3d55,0x3d800000,0xbcc43d6d,0xbd35bd35,0x3d6dbcc4,0x3d0e3d55,0xbd7b3c48,0x3c48bd7b,0x3d553d0e,
0x3c48bd7b,0x3d0ebd55,0x3d55bd0e,0x3d7bbc48,0xbd80,0x3cc4bd6d,0x3d35bd35,0x3d6dbcc4,0xbd7bbc48,0xbd55bd0e,0xbd0ebd55,0xbc48bd7b,0xbd800000,0xbd6dbcc4,0xbd35bd35,0xbcc4bd6d,
0xbc483d7b,0xbd0e3d55,0xbd553d0e,0xbd7b3c48,0x3d80,0xbcc43d6d,0xbd353d35,0xbd6d3cc4,0x3d7b3c48,0x3d553d0e,0x3d0e3d55,0x3c483d7b,0x3d800000,0x3d6d3cc4,0x3d353d35,0x3cc43d6d,
0x3d80,0x3d80,0x3d80,0x3d80,0x3d80,0x3d80,0x3d80,0x3d80,0x3d80,0x3d80,0x3d80,0x3d80,0x3d80,0x3d80,0x3d80,0x3d80,
0x3d80,0x3d80,0x3d80,0x3d80,0x3d80,0x3d80,0x3d80,0x3d80,0x3d80,0x3d80,0x3d80,0x3d80,0x3d80,0x3d80,0x3d80,0x3d80,
0xbd353d35,0xbd553d0e,0xbd6d3cc4,0xbd7b3c48,0x3d80,0xbc483d7b,0xbcc43d6d,0xbd0e3d55,0xbd35bd35,0xbd0ebd55,0xbcc4bd6d,0xbc48bd7b,0xbd800000,0xbd7bbc48,0xbd6dbcc4,0xbd55bd0e,
0x3d35bd35,0x3d55bd0e,0x3d6dbcc4,0x3d7bbc48,0xbd80,0x3c48bd7b,0x3cc4bd6d,0x3d0ebd55,0x3d353d35,0x3d0e3d55,0x3cc43d6d,0x3c483d7b,0x3d800000,0x3d7b3c48,0x3d6d3cc4,0x3d553d0e,
0xbd80,0x3cc4bd6d,0x3d35bd35,0x3d6dbcc4,0x3d800000,0x3d6d3cc4,0x3d353d35,0x3cc43d6d,0x3d80,0xbcc43d6d,0xbd353d35,0xbd6d3cc4,0xbd800000,0xbd6dbcc4,0xbd35bd35,0xbcc4bd6d,
0xbd80,0x3cc4bd6d,0x3d35bd35,0x3d6dbcc4,0x3d800000,0x3d6d3cc4,0x3d353d35,0x3cc43d6d,0x3d80,0xbcc43d6d,0xbd353d35,0xbd6d3cc4,0xbd800000,0xbd6dbcc4,0xbd35bd35,0xbcc4bd6d,
0xbd353d35,0xbd7b3c48,0xbd6dbcc4,0xbd0ebd55,0x3d800000,0x3d553d0e,0x3cc43d6d,0xbc483d7b,0xbd35bd35,0xbc48bd7b,0x3cc4bd6d,0x3d55bd0e,0x3d80,0xbd0e3d55,0xbd6d3cc4,0xbd7bbc48,
0x3d35bd35,0x3d7bbc48,0x3d6d3cc4,0x3d0e3d55,0xbd800000,0xbd55bd0e,0xbcc4bd6d,0x3c48bd7b,0x3d353d35,0x3c483d7b,0xbcc43d6d,0xbd553d0e,0xbd80,0x3d0ebd55,0x3d6dbcc4,0x3d7b3c48,
0x3d80,0xbd353d35,0xbd800000,0xbd35bd35,0xbd80,0x3d35bd35,0x3d800000,0x3d353d35,0x3d80,0xbd353d35,0xbd800000,0xbd35bd35,0xbd80,0x3d35bd35,0x3d800000,0x3d353d35,
0x3d80,0xbd353d35,0xbd800000,0xbd35bd35,0xbd80,0x3d35bd35,0x3d800000,0x3d353d35,0x3d80,0xbd353d35,0xbd800000,0xbd35bd35,0xbd80,0x3d35bd35,0x3d800000,0x3d353d35,
0xbd353d35,0xbd7bbc48,0xbcc4bd6d,0x3d0ebd55,0xbd80,0x3d55bd0e,0x3d6d3cc4,0x3c483d7b,0xbd35bd35,0x3c48bd7b,0x3d6dbcc4,0x3d553d0e,0x3d800000,0x3d0e3d55,0xbcc43d6d,0xbd7b3c48,
0x3d35bd35,0x3d7b3c48,0x3cc43d6d,0xbd0e3d55,0x3d80,0xbd553d0e,0xbd6dbcc4,0xbc48bd7b,0x3d353d35,0xbc483d7b,0xbd6d3cc4,0xbd55bd0e,0xbd800000,0xbd0ebd55,0x3cc4bd6d,0x3d7bbc48,
0xbd80,0x3d6dbcc4,0x3d353d35,0xbcc43d6d,0xbd800000,0xbcc4bd6d,0x3d35bd35,0x3d6d3cc4,0x3d80,0xbd6d3cc4,0xbd35bd35,0x3cc4bd6d,0x3d800000,0x3cc43d6d,0xbd353d35,0xbd6dbcc4,
0xbd80,0x3d6dbcc4,0x3d353d35,0xbcc43d6d,0xbd800000,0xbcc4bd6d,0x3d35bd35,0x3d6d3cc4,0x3d80,0xbd6d3cc4,0xbd35bd35,0x3cc4bd6d,0x3d800000,0x3cc43d6d,0xbd353d35,0xbd6dbcc4,
0xbd353d35,0xbd55bd0e,0x3cc4bd6d,0x3d7b3c48,0xbd800000,0xbc48bd7b,0x3d6dbcc4,0x3d0e3d55,0xbd35bd35,0x3d0ebd55,0x3d6d3cc4,0xbc483d7b,0xbd80,0x3d7bbc48,0x3cc43d6d,0xbd553d0e,
0x3d35bd35,0x3d553d0e,0xbcc43d6d,0xbd7bbc48,0x3d800000,0x3c483d7b,0xbd6d3cc4,0xbd0ebd55,0x3d353d35,0xbd0e3d55,0xbd6dbcc4,0x3c48bd7b,0x3d80,0xbd7b3c48,0xbcc4bd6d,0x3d55bd0e,
0xbd800000,0xbd800000,0xbd800000,0xbd800000,0xbd800000,0xbd800000,0xbd800000,0xbd800000,0xbd800000,0xbd800000,0xbd800000,0xbd800000,0xbd800000,0xbd800000,0xbd800000,0xbd800000,
0xbd800000,0xbd800000,0xbd800000,0xbd800000,0xbd800000,0xbd800000,0xbd800000,0xbd800000,0xbd800000,0xbd800000,0xbd800000,0xbd800000,0xbd800000,0xbd800000,0xbd800000,0xbd800000,
0xbd35bd35,0xbd0ebd55,0xbcc4bd6d,0xbc48bd7b,0xbd800000,0xbd7bbc48,0xbd6dbcc4,0xbd55bd0e,0x3d35bd35,0x3d55bd0e,0x3d6dbcc4,0x3d7bbc48,0x8000bd80,0x3c48bd7b,0x3cc4bd6d,0x3d0ebd55,
0x3d353d35,0x3d0e3d55,0x3cc43d6d,0x3c483d7b,0x3d800000,0x3d7b3c48,0x3d6d3cc4,0x3d553d0e,0xbd353d35,0xbd553d0e,0xbd6d3cc4,0xbd7b3c48,0x80003d80,0xbc483d7b,0xbcc43d6d,0xbd0e3d55,
0x3d800000,0x3d6d3cc4,0x3d353d35,0x3cc43d6d,0x80003d80,0xbcc43d6d,0xbd353d35,0xbd6d3cc4,0xbd800000,0xbd6dbcc4,0xbd35bd35,0xbcc4bd6d,0x8000bd80,0x3cc4bd6d,0x3d35bd35,0x3d6dbcc4,
0x3d800000,0x3d6d3cc4,0x3d353d35,0x3cc43d6d,0x80003d80,0xbcc43d6d,0xbd353d35,0xbd6d3cc4,0xbd800000,0xbd6dbcc4,0xbd35bd35,0xbcc4bd6d,0x8000bd80,0x3cc4bd6d,0x3d35bd35,0x3d6dbcc4,
0xbd35bd35,0xbc48bd7b,0x3cc4bd6d,0x3d55bd0e,0x80003d80,0xbd0e3d55,0xbd6d3cc4,0xbd7bbc48,0x3d35bd35,0x3d7bbc48,0x3d6d3cc4,0x3d0e3d55,0xbd800000,0xbd55bd0e,0xbcc4bd6d,0x3c48bd7b,
0x3d353d35,0x3c483d7b,0xbcc43d6d,0xbd553d0e,0x8000bd80,0x3d0ebd55,0x3d6dbcc4,0x3d7b3c48,0xbd353d35,0xbd7b3c48,0xbd6dbcc4,0xbd0ebd55,0x3d800000,0x3d553d0e,0x3cc43d6d,0xbc483d7b,
0xbd800000,0xbd35bd35,0x8000bd80,0x3d35bd35,0x3d800000,0x3d353d35,0x80003d80,0xbd353d35,0xbd800000,0xbd35bd35,0x8000bd80,0x3d35bd35,0x3d800000,0x3d353d35,0x80003d80,0xbd353d35,
0xbd800000,0xbd35bd35,0x8000bd80,0x3d35bd35,0x3d800000,0x3d353d35,0x80003d80,0xbd353d35,0xbd800000,0xbd35bd35,0x8000bd80,0x3d35bd35,0x3d800000,0x3d353d35,0x80003d80,0xbd353d35,
0xbd35bd35,0x3c48bd7b,0x3d6dbcc4,0x3d553d0e,0x3d800000,0x3d0e3d55,0xbcc43d6d,0xbd7b3c48,0x3d35bd35,0x3d7b3c48,0x3cc43d6d,0xbd0e3d55,0x80003d80,0xbd553d0e,0xbd6dbcc4,0xbc48bd7b,
0x3d353d35,0xbc483d7b,0xbd6d3cc4,0xbd55bd0e,0xbd800000,0xbd0ebd55,0x3cc4bd6d,0x3d7bbc48,0xbd353d35,0xbd7bbc48,0xbcc4bd6d,0x3d0ebd55,0x8000bd80,0x3d55bd0e,0x3d6d3cc4,0x3c483d7b,
0x3d800000,0x3cc43d6d,0xbd353d35,0xbd6dbcc4,0x8000bd80,0x3d6dbcc4,0x3d353d35,0xbcc43d6d,0xbd800000,0xbcc4bd6d,0x3d35bd35,0x3d6d3cc4,0x80003d80,0xbd6d3cc4,0xbd35bd35,0x3cc4bd6d,
0x3d800000,0x3cc43d6d,0xbd353d35,0xbd6dbcc4,0x8000bd80,0x3d6dbcc4,0x3d353d35,0xbcc43d6d,0xbd800000,0xbcc4bd6d,0x3d35bd35,0x3d6d3cc4,0x80003d80,0xbd6d3cc4,0xbd35bd35,0x3cc4bd6d,
0xbd35bd35,0x3d0ebd55,0x3d6d3cc4,0xbc483d7b,0x8000bd80,0x3d7bbc48,0x3cc43d6d,0xbd553d0e,0x3d35bd35,0x3d553d0e,0xbcc43d6d,0xbd7bbc48,0x3d800000,0x3c483d7b,0xbd6d3cc4,0xbd0ebd55,
0x3d353d35,0xbd0e3d55,0xbd6dbcc4,0x3c48bd7b,0x80003d80,0xbd7b3c48,0xbcc4bd6d,0x3d55bd0e,0xbd353d35,0xbd55bd0e,0x3cc4bd6d,0x3d7b3c48,0xbd800000,0xbc48bd7b,0x3d6dbcc4,0x3d0e3d55,
0x3d80,0xbd800000,0xbd80,0x3d800000,0x3d80,0xbd800000,0xbd80,0x3d800000,0x3d80,0xbd800000,0xbd80,0x3d800000,0x3d80,0xbd800000,0xbd80,0x3d800000,
0x3d80,0xbd800000,0xbd80,0x3d800000,0x3d80,0xbd800000,0xbd80,0x3d800000,0x3d80,0xbd800000,0xbd80,0x3d800000,0x3d80,0xbd800000,0xbd80,0x3d800000,
0xbd353d35,0xbd0ebd55,0x3d6dbcc4,0x3c483d7b,0x3d80,0xbd7bbc48,0x3cc4bd6d,0x3d553d0e,0xbd35bd35,0x3d55bd0e,0x3cc43d6d,0xbd7b3c48,0xbd800000,0x3c48bd7b,0x3d6d3cc4,0xbd0e3d55,
0x3d35bd35,0x3d0e3d55,0xbd6d3cc4,0xbc48bd7b,0xbd80,0x3d7b3c48,0xbcc43d6d,0xbd55bd0e,0x3d353d35,0xbd553d0e,0xbcc4bd6d,0x3d7bbc48,0x3d800000,0xbc483d7b,0xbd6dbcc4,0x3d0ebd55,
0xbd80,0x3d6d3cc4,0xbd353d35,0xbcc4bd6d,0x3d800000,0xbcc43d6d,0xbd35bd35,0x3d6dbcc4,0x3d80,0xbd6dbcc4,0x3d35bd35,0x3cc43d6d,0xbd800000,0x3cc4bd6d,0x3d353d35,0xbd6d3cc4,
0xbd80,0x3d6d3cc4,0xbd353d35,0xbcc4bd6d,0x3d800000,0xbcc43d6d,0xbd35bd35,0x3d6dbcc4,0x3d80,0xbd6dbcc4,0x3d35bd35,0x3cc43d6d,0xbd800000,0x3cc4bd6d,0x3d353d35,0xbd6d3cc4,
0xbd353d35,0xbc48bd7b,0x3d6d3cc4,0xbd553d0e,0x3d800000,0xbd0e3d55,0xbcc4bd6d,0x3d7b3c48,0xbd35bd35,0x3d7bbc48,0xbcc43d6d,0xbd0ebd55,0x3d80,0xbd55bd0e,0x3d6dbcc4,0xbc483d7b,
0x3d35bd35,0x3c483d7b,0xbd6dbcc4,0x3d55bd0e,0xbd800000,0x3d0ebd55,0x3cc43d6d,0xbd7bbc48,0x3d353d35,0xbd7b3c48,0x3cc4bd6d,0x3d0e3d55,0xbd80,0x3d553d0e,0xbd6d3cc4,0x3c48bd7b,
0x3d80,0xbd35bd35,0x3d800000,0xbd353d35,0xbd80,0x3d353d35,0xbd800000,0x3d35bd35,0x3d80,0xbd35bd35,0x3d800000,0xbd353d35,0xbd80,0x3d353d35,0xbd800000,0x3d35bd35,
0x3d80,0xbd35bd35,0x3d800000,0xbd353d35,0xbd80,0x3d353d35,0xbd800000,0x3d35bd35,0x3d80,0xbd35bd35,0x3d800000,0xbd353d35,0xbd80,0x3d353d35,0xbd800000,0x3d35bd35,
0xbd353d35,0x3c48bd7b,0x3cc43d6d,0xbd55bd0e,0xbd80,0x3d0e3d55,0xbd6dbcc4,0x3d7bbc48,0xbd35bd35,0x3d7b3c48,0xbd6d3cc4,0x3d0ebd55,0x3d800000,0xbd553d0e,0x3cc4bd6d,0x3c483d7b,
0x3d35bd35,0xbc483d7b,0xbcc4bd6d,0x3d553d0e,0x3d80,0xbd0ebd55,0x3d6d3cc4,0xbd7b3c48,0x3d353d35,0xbd7bbc48,0x3d6dbcc4,0xbd0e3d55,0xbd800000,0x3d55bd0e,0xbcc43d6d,0xbc48bd7b,
0xbd80,0x3cc43d6d,0xbd35bd35,0x3d6d3cc4,0xbd800000,0x3d6dbcc4,0xbd353d35,0x3cc4bd6d,0x3d80,0xbcc4bd6d,0x3d353d35,0xbd6dbcc4,0x3d800000,0xbd6d3cc4,0x3d35bd35,0xbcc43d6d,
0xbd80,0x3cc43d6d,0xbd35bd35,0x3d6d3cc4,0xbd800000,0x3d6dbcc4,0xbd353d35,0x3cc4bd6d,0x3d80,0xbcc4bd6d,0x3d353d35,0xbd6dbcc4,0x3d800000,0xbd6d3cc4,0x3d35bd35,0xbcc43d6d,
0xbd353d35,0x3d0ebd55,0xbcc43d6d,0x3c48bd7b,0xbd800000,0x3d7bbc48,0xbd6d3cc4,0x3d55bd0e,0xbd35bd35,0x3d553d0e,0xbd6dbcc4,0x3d7b3c48,0xbd80,0x3c483d7b,0xbcc4bd6d,0x3d0e3d55,
0x3d35bd35,0xbd0e3d55,0x3cc4bd6d,0xbc483d7b,0x3d800000,0xbd7b3c48,0x3d6dbcc4,0xbd553d0e,0x3d353d35,0xbd55bd0e,0x3d6d3cc4,0xbd7bbc48,0x3d80,0xbc48bd7b,0x3cc43d6d,0xbd0ebd55,
0xbd800000,0x8000bd80,0x3d800000,0x80003d80,0xbd800000,0x8000bd80,0x3d800000,0x80003d80,0xbd800000,0x8000bd80,0x3d800000,0x80003d80,0xbd800000,0x8000bd80,0x3d800000,0x80003d80,
0xbd800000,0x8000bd80,0x3d800000,0x80003d80,0xbd800000,0x8000bd80,0x3d800000,0x80003d80,0xbd800000,0x8000bd80,0x3d800000,0x80003d80,0xbd800000,0x8000bd80,0x3d800000,0x80003d80,
0xbd35bd35,0x3d55bd0e,0x3cc43d6d,0xbd7b3c48,0xbd800000,0x3c48bd7b,0x3d6d3cc4,0xbd0e3d55,0x3d35bd35,0x3d0e3d55,0xbd6d3cc4,0xbc48bd7b,0x8000bd80,0x3d7b3c48,0xbcc43d6d,0xbd55bd0e,
0x3d353d35,0xbd553d0e,0xbcc4bd6d,0x3d7bbc48,0x3d800000,0xbc483d7b,0xbd6dbcc4,0x3d0ebd55,0xbd353d35,0xbd0ebd55,0x3d6dbcc4,0x3c483d7b,0x80003d80,0xbd7bbc48,0x3cc4bd6d,0x3d553d0e,
0x3d800000,0xbcc43d6d,0xbd35bd35,0x3d6dbcc4,0x80003d80,0xbd6dbcc4,0x3d35bd35,0x3cc43d6d,0xbd800000,0x3cc4bd6d,0x3d353d35,0xbd6d3cc4,0x8000bd80,0x3d6d3cc4,0xbd353d35,0xbcc4bd6d,
0x3d800000,0xbcc43d6d,0xbd35bd35,0x3d6dbcc4,0x80003d80,0xbd6dbcc4,0x3d35bd35,0x3cc43d6d,0xbd800000,0x3cc4bd6d,0x3d353d35,0xbd6d3cc4,0x8000bd80,0x3d6d3cc4,0xbd353d35,0xbcc4bd6d,
0xbd35bd35,0x3d7bbc48,0xbcc43d6d,0xbd0ebd55,0x80003d80,0xbd55bd0e,0x3d6dbcc4,0xbc483d7b,0x3d35bd35,0x3c483d7b,0xbd6dbcc4,0x3d55bd0e,0xbd800000,0x3d0ebd55,0x3cc43d6d,0xbd7bbc48,
0x3d353d35,0xbd7b3c48,0x3cc4bd6d,0x3d0e3d55,0x8000bd80,0x3d553d0e,0xbd6d3cc4,0x3c48bd7b,0xbd353d35,0xbc48bd7b,0x3d6d3cc4,0xbd553d0e,0x3d800000,0xbd0e3d55,0xbcc4bd6d,0x3d7b3c48,
0xbd800000,0x3d35bd35,0x80003d80,0xbd35bd35,0x3d800000,0xbd353d35,0x8000bd80,0x3d353d35,0xbd800000,0x3d35bd35,0x80003d80,0xbd35bd35,0x3d800000,0xbd353d35,0x8000bd80,0x3d353d35,
0xbd800000,0x3d35bd35,0x80003d80,0xbd35bd35,0x3d800000,0xbd353d35,0x8000bd80,0x3d353d35,0xbd800000,0x3d35bd35,0x80003d80,0xbd35bd35,0x3d800000,0xbd353d35,0x8000bd80,0x3d353d35,
0xbd35bd35,0x3d7b3c48,0xbd6d3cc4,0x3d0ebd55,0x3d800000,0xbd553d0e,0x3cc4bd6d,0x3c483d7b,0x3d35bd35,0xbc483d7b,0xbcc4bd6d,0x3d553d0e,0x80003d80,0xbd0ebd55,0x3d6d3cc4,0xbd7b3c48,
0x3d353d35,0xbd7bbc48,0x3d6dbcc4,0xbd0e3d55,0xbd800000,0x3d55bd0e,0xbcc43d6d,0xbc48bd7b,0xbd353d35,0x3c48bd7b,0x3cc43d6d,0xbd55bd0e,0x8000bd80,0x3d0e3d55,0xbd6dbcc4,0x3d7bbc48,
0x3d800000,0xbd6d3cc4,0x3d35bd35,0xbcc43d6d,0x8000bd80,0x3cc43d6d,0xbd35bd35,0x3d6d3cc4,0xbd800000,0x3d6dbcc4,0xbd353d35,0x3cc4bd6d,0x80003d80,0xbcc4bd6d,0x3d353d35,0xbd6dbcc4,
0x3d800000,0xbd6d3cc4,0x3d35bd35,0xbcc43d6d,0x8000bd80,0x3cc43d6d,0xbd35bd35,0x3d6d3cc4,0xbd800000,0x3d6dbcc4,0xbd353d35,0x3cc4bd6d,0x80003d80,0xbcc4bd6d,0x3d353d35,0xbd6dbcc4,
0xbd35bd35,0x3d553d0e,0xbd6dbcc4,0x3d7b3c48,0x8000bd80,0x3c483d7b,0xbcc4bd6d,0x3d0e3d55,0x3d35bd35,0xbd0e3d55,0x3cc4bd6d,0xbc483d7b,0x3d800000,0xbd7b3c48,0x3d6dbcc4,0xbd553d0e,
0x3d353d35,0xbd55bd0e,0x3d6d3cc4,0xbd7bbc48,0x80003d80,0xbc48bd7b,0x3cc43d6d,0xbd0ebd55,0xbd353d35,0x3d0ebd55,0xbcc43d6d,0x3c48bd7b,0xbd800000,0x3d7bbc48,0xbd6d3cc4,0x3d55bd0e,
0x3d80,0xbd80,0x3d80,0xbd80,0x3d80,0xbd80,0x3d80,0xbd80,0x3d80,0xbd80,0x3d80,0xbd80,0x3d80,0xbd80,0x3d80,0xbd80,
0x3d80,0xbd80,0x3d80,0xbd80,0x3d80,0xbd80,0x3d80,0xbd80,0x3d80,0xbd80,0x3d80,0xbd80,0x3d80,0xbd80,0x3d80,0xbd80,
0xbd353d35,0x3d55bd0e,0xbd6d3cc4,0x3d7bbc48,0x3d80,0x3c48bd7b,0xbcc43d6d,0x3d0ebd55,0xbd35bd35,0x3d0e3d55,0xbcc4bd6d,0x3c483d7b,0xbd800000,0x3d7b3c48,0xbd6dbcc4,0x3d553d0e,
0x3d35bd35,0xbd553d0e,0x3d6dbcc4,0xbd7b3c48,0xbd80,0xbc483d7b,0x3cc4bd6d,0xbd0e3d55,0x3d353d35,0xbd0ebd55,0x3cc43d6d,0xbc48bd7b,0x3d800000,0xbd7bbc48,0x3d6d3cc4,0xbd55bd0e,
0xbd80,0xbcc43d6d,0x3d35bd35,0xbd6d3cc4,0x3d800000,0xbd6dbcc4,0x3d353d35,0xbcc4bd6d,0x3d80,0x3cc4bd6d,0xbd353d35,0x3d6dbcc4,0xbd800000,0x3d6d3cc4,0xbd35bd35,0x3cc43d6d,
0xbd80,0xbcc43d6d,0x3d35bd35,0xbd6d3cc4,0x3d800000,0xbd6dbcc4,0x3d353d35,0xbcc4bd6d,0x3d80,0x3cc4bd6d,0xbd353d35,0x3d6dbcc4,0xbd800000,0x3d6d3cc4,0xbd35bd35,0x3cc43d6d,
0xbd353d35,0x3d7bbc48,0xbd6dbcc4,0x3d0e3d55,0x3d800000,0xbd55bd0e,0x3cc43d6d,0x3c48bd7b,0xbd35bd35,0x3c483d7b,0x3cc4bd6d,0xbd553d0e,0x3d80,0x3d0ebd55,0xbd6d3cc4,0x3d7b3c48,
0x3d35bd35,0xbd7b3c48,0x3d6d3cc4,0xbd0ebd55,0xbd800000,0x3d553d0e,0xbcc4bd6d,0xbc483d7b,0x3d353d35,0xbc48bd7b,0xbcc43d6d,0x3d55bd0e,0xbd80,0xbd0e3d55,0x3d6dbcc4,0xbd7bbc48,
0x3d80,0x3d35bd35,0xbd800000,0x3d353d35,0xbd80,0xbd353d35,0x3d800000,0xbd35bd35,0x3d80,0x3d35bd35,0xbd800000,0x3d353d35,0xbd80,0xbd353d35,0x3d800000,0xbd35bd35,
0x3d80,0x3d35bd35,0xbd800000,0x3d353d35,0xbd80,0xbd353d35,0x3d800000,0xbd35bd35,0x3d80,0x3d35bd35,0xbd800000,0x3d353d35,0xbd80,0xbd353d35,0x3d800000,0xbd35bd35,
0xbd353d35,0x3d7b3c48,0xbcc4bd6d,0xbd0e3d55,0xbd80,0xbd553d0e,0x3d6d3cc4,0xbc48bd7b,0xbd35bd35,0xbc483d7b,0x3d6dbcc4,0xbd55bd0e,0x3d800000,0xbd0ebd55,0xbcc43d6d,0x3d7bbc48,
0x3d35bd35,0xbd7bbc48,0x3cc43d6d,0x3d0ebd55,0x3d80,0x3d55bd0e,0xbd6dbcc4,0x3c483d7b,0x3d353d35,0x3c48bd7b,0xbd6d3cc4,0x3d553d0e,0xbd800000,0x3d0e3d55,0x3cc4bd6d,0xbd7b3c48,
0xbd80,0xbd6d3cc4,0x3d353d35,0x3cc4bd6d,0xbd800000,0x3cc43d6d,0x3d35bd35,0xbd6dbcc4,0x3d80,0x3d6dbcc4,0xbd35bd35,0xbcc43d6d,0x3d800000,0xbcc4bd6d,0xbd353d35,0x3d6d3cc4,
0xbd80,0xbd6d3cc4,0x3d353d35,0x3cc4bd6d,0xbd800000,0x3cc43d6d,0x3d35bd35,0xbd6dbcc4,0x3d80,0x3d6dbcc4,0xbd35bd35,0xbcc43d6d,0x3d800000,0xbcc4bd6d,0xbd353d35,0x3d6d3cc4,
0xbd353d35,0x3d553d0e,0x3cc4bd6d,0xbd7bbc48,0xbd800000,0x3c483d7b,0x3d6dbcc4,0xbd0ebd55,0xbd35bd35,0xbd0e3d55,0x3d6d3cc4,0x3c48bd7b,0xbd80,0xbd7b3c48,0x3cc43d6d,0x3d55bd0e,
0x3d35bd35,0xbd55bd0e,0xbcc43d6d,0x3d7b3c48,0x3d800000,0xbc48bd7b,0xbd6d3cc4,0x3d0e3d55,0x3d353d35,0x3d0ebd55,0xbd6dbcc4,0xbc483d7b,0x3d80,0x3d7bbc48,0xbcc4bd6d,0xbd553d0e,
0xbd800000,0x3d800000,0xbd800000,0x3d800000,0xbd800000,0x3d800000,0xbd800000,0x3d800000,0xbd800000,0x3d800000,0xbd800000,0x3d800000,0xbd800000,0x3d800000,0xbd800000,0x3d800000,
0xbd800000,0x3d800000,0xbd800000,0x3d800000,0xbd800000,0x3d800000,0xbd800000,0x3d800000,0xbd800000,0x3d800000,0xbd800000,0x3d800000,0xbd800000,0x3d800000,0xbd800000,0x3d800000,
0xbd35bd35,0x3d0e3d55,0xbcc4bd6d,0x3c483d7b,0xbd800000,0x3d7b3c48,0xbd6dbcc4,0x3d553d0e,0x3d35bd35,0xbd553d0e,0x3d6dbcc4,0xbd7b3c48,0x8000bd80,0xbc483d7b,0x3cc4bd6d,0xbd0e3d55,
0x3d353d35,0xbd0ebd55,0x3cc43d6d,0xbc48bd7b,0x3d800000,0xbd7bbc48,0x3d6d3cc4,0xbd55bd0e,0xbd353d35,0x3d55bd0e,0xbd6d3cc4,0x3d7bbc48,0x80003d80,0x3c48bd7b,0xbcc43d6d,0x3d0ebd55,
0x3d800000,0xbd6dbcc4,0x3d353d35,0xbcc4bd6d,0x80003d80,0x3cc4bd6d,0xbd353d35,0x3d6dbcc4,0xbd800000,0x3d6d3cc4,0xbd35bd35,0x3cc43d6d,0x8000bd80,0xbcc43d6d,0x3d35bd35,0xbd6d3cc4,
0x3d800000,0xbd6dbcc4,0x3d353d35,0xbcc4bd6d,0x80003d80,0x3cc4bd6d,0xbd353d35,0x3d6dbcc4,0xbd800000,0x3d6d3cc4,0xbd35bd35,0x3cc43d6d,0x8000bd80,0xbcc43d6d,0x3d35bd35,0xbd6d3cc4,
0xbd35bd35,0x3c483d7b,0x3cc4bd6d,0xbd553d0e,0x80003d80,0x3d0ebd55,0xbd6d3cc4,0x3d7b3c48,0x3d35bd35,0xbd7b3c48,0x3d6d3cc4,0xbd0ebd55,0xbd800000,0x3d553d0e,0xbcc4bd6d,0xbc483d7b,
0x3d353d35,0xbc48bd7b,0xbcc43d6d,0x3d55bd0e,0x8000bd80,0xbd0e3d55,0x3d6dbcc4,0xbd7bbc48,0xbd353d35,0x3d7bbc48,0xbd6dbcc4,0x3d0e3d55,0x3d800000,0xbd55bd0e,0x3cc43d6d,0x3c48bd7b,
0xbd800000,0x3d353d35,0x8000bd80,0xbd353d35,0x3d800000,0xbd35bd35,0x80003d80,0x3d35bd35,0xbd800000,0x3d353d35,0x8000bd80,0xbd353d35,0x3d800000,0xbd35bd35,0x80003d80,0x3d35bd35,
0xbd800000,0x3d353d35,0x8000bd80,0xbd353d35,0x3d800000,0xbd35bd35,0x80003d80,0x3d35bd35,0xbd800000,0x3d353d35,0x8000bd80,0xbd353d35,0x3d800000,0xbd35bd35,0x80003d80,0x3d35bd35,
0xbd35bd35,0xbc483d7b,0x3d6dbcc4,0xbd55bd0e,0x3d800000,0xbd0ebd55,0xbcc43d6d,0x3d7bbc48,0x3d35bd35,0xbd7bbc48,0x3cc43d6d,0x3d0ebd55,0x80003d80,0x3d55bd0e,0xbd6dbcc4,0x3c483d7b,
0x3d353d35,0x3c48bd7b,0xbd6d3cc4,0x3d553d0e,0xbd800000,0x3d0e3d55,0x3cc4bd6d,0xbd7b3c48,0xbd353d35,0x3d7b3c48,0xbcc4bd6d,0xbd0e3d55,0x8000bd80,0xbd553d0e,0x3d6d3cc4,0xbc48bd7b,
0x3d800000,0xbcc4bd6d,0xbd353d35,0x3d6d3cc4,0x8000bd80,0xbd6d3cc4,0x3d353d35,0x3cc4bd6d,0xbd800000,0x3cc43d6d,0x3d35bd35,0xbd6dbcc4,0x80003d80,0x3d6dbcc4,0xbd35bd35,0xbcc43d6d,
0x3d800000,0xbcc4bd6d,0xbd353d35,0x3d6d3cc4,0x8000bd80,0xbd6d3cc4,0x3d353d35,0x3cc4bd6d,0xbd800000,0x3cc43d6d,0x3d35bd35,0xbd6dbcc4,0x80003d80,0x3d6dbcc4,0xbd35bd35,0xbcc43d6d,
0xbd35bd35,0xbd0e3d55,0x3d6d3cc4,0x3c48bd7b,0x8000bd80,0xbd7b3c48,0x3cc43d6d,0x3d55bd0e,0x3d35bd35,0xbd55bd0e,0xbcc43d6d,0x3d7b3c48,0x3d800000,0xbc48bd7b,0xbd6d3cc4,0x3d0e3d55,
0x3d353d35,0x3d0ebd55,0xbd6dbcc4,0xbc483d7b,0x80003d80,0x3d7bbc48,0xbcc4bd6d,0xbd553d0e,0xbd353d35,0x3d553d0e,0x3cc4bd6d,0xbd7bbc48,0xbd800000,0x3c483d7b,0x3d6dbcc4,0xbd0ebd55,
0x3d80,0x3d800000,0xbd80,0xbd800000,0x3d80,0x3d800000,0xbd80,0xbd800000,0x3d80,0x3d800000,0xbd80,0xbd800000,0x3d80,0x3d800000,0xbd80,0xbd800000,
0x3d80,0x3d800000,0xbd80,0xbd800000,0x3d80,0x3d800000,0xbd80,0xbd800000,0x3d80,0x3d800000,0xbd80,0xbd800000,0x3d80,0x3d800000,0xbd80,0xbd800000,
0xbd353d35,0x3d0e3d55,0x3d6dbcc4,0xbc48bd7b,0x3d80,0x3d7b3c48,0x3cc4bd6d,0xbd55bd0e,0xbd35bd35,0xbd553d0e,0x3cc43d6d,0x3d7bbc48,0xbd800000,0xbc483d7b,0x3d6d3cc4,0x3d0ebd55,
0x3d35bd35,0xbd0ebd55,0xbd6d3cc4,0x3c483d7b,0xbd80,0xbd7bbc48,0xbcc43d6d,0x3d553d0e,0x3d353d35,0x3d55bd0e,0xbcc4bd6d,0xbd7b3c48,0x3d800000,0x3c48bd7b,0xbd6dbcc4,0xbd0e3d55,
0xbd80,0xbd6dbcc4,0xbd353d35,0x3cc43d6d,0x3d800000,0x3cc4bd6d,0xbd35bd35,0xbd6d3cc4,0x3d80,0x3d6d3cc4,0x3d35bd35,0xbcc4bd6d,0xbd800000,0xbcc43d6d,0x3d353d35,0x3d6dbcc4,
0xbd80,0xbd6dbcc4,0xbd353d35,0x3cc43d6d,0x3d800000,0x3cc4bd6d,0xbd35bd35,0xbd6d3cc4,0x3d80,0x3d6d3cc4,0x3d35bd35,0xbcc4bd6d,0xbd800000,0xbcc43d6d,0x3d353d35,0x3d6dbcc4,
0xbd353d35,0x3c483d7b,0x3d6d3cc4,0x3d55bd0e,0x3d800000,0x3d0ebd55,0xbcc4bd6d,0xbd7bbc48,0xbd35bd35,0xbd7b3c48,0xbcc43d6d,0x3d0e3d55,0x3d80,0x3d553d0e,0x3d6dbcc4,0x3c48bd7b,
0x3d35bd35,0xbc48bd7b,0xbd6dbcc4,0xbd553d0e,0xbd800000,0xbd0e3d55,0x3cc43d6d,0x3d7b3c48,0x3d353d35,0x3d7bbc48,0x3cc4bd6d,0xbd0ebd55,0xbd80,0xbd55bd0e,0xbd6d3cc4,0xbc483d7b,
0x3d80,0x3d353d35,0x3d800000,0x3d35bd35,0xbd80,0xbd35bd35,0xbd800000,0xbd353d35,0x3d80,0x3d353d35,0x3d800000,0x3d35bd35,0xbd80,0xbd35bd35,0xbd800000,0xbd353d35,
0x3d80,0x3d353d35,0x3d800000,0x3d35bd35,0xbd80,0xbd35bd35,0xbd800000,0xbd353d35,0x3d80,0x3d353d35,0x3d800000,0x3d35bd35,0xbd80,0xbd35bd35,0xbd800000,0xbd353d35,
0xbd353d35,0xbc483d7b,0x3cc43d6d,0x3d553d0e,0xbd80,0xbd0ebd55,0xbd6dbcc4,0xbd7b3c48,0xbd35bd35,0xbd7bbc48,0xbd6d3cc4,0xbd0e3d55,0x3d800000,0x3d55bd0e,0x3cc4bd6d,0xbc48bd7b,
0x3d35bd35,0x3c48bd7b,0xbcc4bd6d,0xbd55bd0e,0x3d80,0x3d0e3d55,0x3d6d3cc4,0x3d7bbc48,0x3d353d35,0x3d7b3c48,0x3d6dbcc4,0x3d0ebd55,0xbd800000,0xbd553d0e,0xbcc43d6d,0x3c483d7b,
0xbd80,0xbcc4bd6d,0xbd35bd35,0xbd6dbcc4,0xbd800000,0xbd6d3cc4,0xbd353d35,0xbcc43d6d,0x3d80,0x3cc43d6d,0x3d353d35,0x3d6d3cc4,0x3d800000,0x3d6dbcc4,0x3d35bd35,0x3cc4bd6d,
0xbd80,0xbcc4bd6d,0xbd35bd35,0xbd6dbcc4,0xbd800000,0xbd6d3cc4,0xbd353d35,0xbcc43d6d,0x3d80,0x3cc43d6d,0x3d353d35,0x3d6d3cc4,0x3d800000,0x3d6dbcc4,0x3d35bd35,0x3cc4bd6d,
0xbd353d35,0xbd0e3d55,0xbcc43d6d,0xbc483d7b,0xbd800000,0xbd7b3c48,0xbd6d3cc4,0xbd553d0e,0xbd35bd35,0xbd55bd0e,0xbd6dbcc4,0xbd7bbc48,0xbd80,0xbc48bd7b,0xbcc4bd6d,0xbd0ebd55,
0x3d35bd35,0x3d0ebd55,0x3cc4bd6d,0x3c48bd7b,0x3d800000,0x3d7bbc48,0x3d6dbcc4,0x3d55bd0e,0x3d353d35,0x3d553d0e,0x3d6d3cc4,0x3d7b3c48,0x3d80,0x3c483d7b,0x3cc43d6d,0x3d0e3d55,
0xbd800000,0x80003d80,0x3d800000,0x8000bd80,0xbd800000,0x80003d80,0x3d800000,0x8000bd80,0xbd800000,0x80003d80,0x3d800000,0x8000bd80,0xbd800000,0x80003d80,0x3d800000,0x8000bd80,
0xbd800000,0x80003d80,0x3d800000,0x8000bd80,0xbd800000,0x80003d80,0x3d800000,0x8000bd80,0xbd800000,0x80003d80,0x3d800000,0x8000bd80,0xbd800000,0x80003d80,0x3d800000,0x8000bd80,
0xbd35bd35,0xbd553d0e,0x3cc43d6d,0x3d7bbc48,0xbd800000,0xbc483d7b,0x3d6d3cc4,0x3d0ebd55,0x3d35bd35,0xbd0ebd55,0xbd6d3cc4,0x3c483d7b,0x8000bd80,0xbd7bbc48,0xbcc43d6d,0x3d553d0e,
0x3d353d35,0x3d55bd0e,0xbcc4bd6d,0xbd7b3c48,0x3d800000,0x3c48bd7b,0xbd6dbcc4,0xbd0e3d55,0xbd353d35,0x3d0e3d55,0x3d6dbcc4,0xbc48bd7b,0x80003d80,0x3d7b3c48,0x3cc4bd6d,0xbd55bd0e,
0x3d800000,0x3cc4bd6d,0xbd35bd35,0xbd6d3cc4,0x80003d80,0x3d6d3cc4,0x3d35bd35,0xbcc4bd6d,0xbd800000,0xbcc43d6d,0x3d353d35,0x3d6dbcc4,0x8000bd80,0xbd6dbcc4,0xbd353d35,0x3cc43d6d,
0x3d800000,0x3cc4bd6d,0xbd35bd35,0xbd6d3cc4,0x80003d80,0x3d6d3cc4,0x3d35bd35,0xbcc4bd6d,0xbd800000,0xbcc43d6d,0x3d353d35,0x3d6dbcc4,0x8000bd80,0xbd6dbcc4,0xbd353d35,0x3cc43d6d,
0xbd35bd35,0xbd7b3c48,0xbcc43d6d,0x3d0e3d55,0x80003d80,0x3d553d0e,0x3d6dbcc4,0x3c48bd7b,0x3d35bd35,0xbc48bd7b,0xbd6dbcc4,0xbd553d0e,0xbd800000,0xbd0e3d55,0x3cc43d6d,0x3d7b3c48,
0x3d353d35,0x3d7bbc48,0x3cc4bd6d,0xbd0ebd55,0x8000bd80,0xbd55bd0e,0xbd6d3cc4,0xbc483d7b,0xbd353d35,0x3c483d7b,0x3d6d3cc4,0x3d55bd0e,0x3d800000,0x3d0ebd55,0xbcc4bd6d,0xbd7bbc48,
0xbd800000,0xbd353d35,0x80003d80,0x3d353d35,0x3d800000,0x3d35bd35,0x8000bd80,0xbd35bd35,0xbd800000,0xbd353d35,0x80003d80,0x3d353d35,0x3d800000,0x3d35bd35,0x8000bd80,0xbd35bd35,
0xbd800000,0xbd353d35,0x80003d80,0x3d353d35,0x3d800000,0x3d35bd35,0x8000bd80,0xbd35bd35,0xbd800000,0xbd353d35,0x80003d80,0x3d353d35,0x3d800000,0x3d35bd35,0x8000bd80,0xbd35bd35,
0xbd35bd35,0xbd7bbc48,0xbd6d3cc4,0xbd0e3d55,0x3d800000,0x3d55bd0e,0x3cc4bd6d,0xbc48bd7b,0x3d35bd35,0x3c48bd7b,0xbcc4bd6d,0xbd55bd0e,0x80003d80,0x3d0e3d55,0x3d6d3cc4,0x3d7bbc48,
0x3d353d35,0x3d7b3c48,0x3d6dbcc4,0x3d0ebd55,0xbd800000,0xbd553d0e,0xbcc43d6d,0x3c483d7b,0xbd353d35,0xbc483d7b,0x3cc43d6d,0x3d553d0e,0x8000bd80,0xbd0ebd55,0xbd6dbcc4,0xbd7b3c48,
0x3d800000,0x3d6dbcc4,0x3d35bd35,0x3cc4bd6d,0x8000bd80,0xbcc4bd6d,0xbd35bd35,0xbd6dbcc4,0xbd800000,0xbd6d3cc4,0xbd353d35,0xbcc43d6d,0x80003d80,0x3cc43d6d,0x3d353d35,0x3d6d3cc4,
0x3d800000,0x3d6dbcc4,0x3d35bd35,0x3cc4bd6d,0x8000bd80,0xbcc4bd6d,0xbd35bd35,0xbd6dbcc4,0xbd800000,0xbd6d3cc4,0xbd353d35,0xbcc43d6d,0x80003d80,0x3cc43d6d,0x3d353d35,0x3d6d3cc4,
0xbd35bd35,0xbd55bd0e,0xbd6dbcc4,0xbd7bbc48,0x8000bd80,0xbc48bd7b,0xbcc4bd6d,0xbd0ebd55,0x3d35bd35,0x3d0ebd55,0x3cc4bd6d,0x3c48bd7b,0x3d800000,0x3d7bbc48,0x3d6dbcc4,0x3d55bd0e,
0x3d353d35,0x3d553d0e,0x3d6d3cc4,0x3d7b3c48,0x80003d80,0x3c483d7b,0x3cc43d6d,0x3d0e3d55,0xbd353d35,0xbd0e3d55,0xbcc43d6d,0xbc483d7b,0xbd800000,0xbd7b3c48,0xbd6d3cc4,0xbd553d0e,
0x3d80,0xbb493d80,0xbbc93d7f,0xbc163d7d,0xbc483d7b,0xbc793d78,0xbc953d75,0xbcac3d71,0xbcc43d6d,0xbcdb3d67,0xbcf13d62,0xbd043d5c,0xbd0e3d55,0xbd183d4e,0xbd223d46,0xbd2c3d3e,
0xbd353d35,0xbd3e3d2c,0xbd463d22,0xbd4e3d18,0xbd553d0e,0xbd5c3d04,0xbd623cf1,0xbd673cdb,0xbd6d3cc4,0xbd713cac,0xbd753c95,0xbd783c79,0xbd7b3c48,0xbd7d3c16,0xbd7f3bc9,0xbd803b49,
0xbd553d0e,0xbd713cac,0xbd7f3bc9,0xbd7dbc16,0x3d80,0xbc793d78,0xbcf13d62,0xbd2c3d3e,0xbc48bd7b,0x3b49bd80,0x3c95bd75,0x3d04bd5c,0xbd6dbcc4,0xbd4ebd18,0xbd22bd46,0xbcdbbd67,
0x3d7b3c48,0x3d673cdb,0x3d463d22,0x3d183d4e,0x3d35bd35,0x3d5cbd04,0x3d75bc95,0x3d80bb49,0xbd0e3d55,0xbd3e3d2c,0xbd623cf1,0xbd783c79,0x3cc43d6d,0x3c163d7d,0xbbc93d7f,0xbcac3d71,
0x3cc4bd6d,0x3d3ebd2c,0x3d75bc95,0x3d7d3c16,0x3d553d0e,0x3d043d5c,0x3bc93d7f,0xbcac3d71,0x3d80,0xbcdb3d67,0xbd463d22,0xbd783c79,0xbd7bbc48,0xbd4ebd18,0xbcf1bd62,0xbb49bd80,
0x3d6dbcc4,0x3d803b49,0x3d623cf1,0x3d183d4e,0x3c483d7b,0xbc793d78,0xbd223d46,0xbd673cdb,0xbd353d35,0xbd713cac,0xbd7fbbc9,0xbd5cbd04,0xbd0ebd55,0xbc16bd7d,0x3c95bd75,0x3d2cbd3e,
0xbd7b3c48,0xbd67bcdb,0xbcf1bd62,0x3c16bd7d,0x3d6d3cc4,0x3d043d5c,0xbbc93d7f,0xbd2c3d3e,0xbd0ebd55,0x3b49bd80,0x3d22bd46,0x3d78bc79,0x3d80,0xbd183d4e,0xbd753c95,0xbd71bcac,
0x3d553d0e,0x3cac3d71,0xbc953d75,0xbd4e3d18,0xbcc4bd6d,0x3c79bd78,0x3d46bd22,0x3d80bb49,0xbc483d7b,0xbd3e3d2c,0xbd7f3bc9,0xbd5cbd04,0x3d35bd35,0x3d7dbc16,0x3d623cf1,0x3cdb3d67,
0xbd353d35,0xbd80bb49,0xbd22bd46,0x3c16bd7d,0x3d55bd0e,0x3d783c79,0x3cf13d62,0xbcac3d71,0xbd6d3cc4,0xbd67bcdb,0xbc95bd75,0x3d04bd5c,0x3d7bbc48,0x3d4e3d18,0x3bc93d7f,0xbd2c3d3e,
0x3d80,0xbd3e3d2c,0xbd7fbbc9,0xbd18bd4e,0x3c48bd7b,0x3d5cbd04,0x3d753c95,0x3cdb3d67,0xbcc43d6d,0xbd713cac,0xbd62bcf1,0xbc79bd78,0x3d0ebd55,0x3d7dbc16,0x3d463d22,0x3b493d80,
0xbd7bbc48,0xbcacbd71,0x3d22bd46,0x3d7d3c16,0x3d35bd35,0x3d783c79,0x3c953d75,0xbd2c3d3e,0x3d0ebd55,0x3d803b49,0x3cf13d62,0xbd043d5c,0x3cc43d6d,0xbd183d4e,0xbd7fbbc9,0xbcdbbd67,
0x3d55bd0e,0x3d673cdb,0x3bc93d7f,0xbd4e3d18,0x3d80,0xbd5c3d04,0xbd62bcf1,0xbb49bd80,0x3c483d7b,0xbd3e3d2c,0xbd75bc95,0xbc79bd78,0xbd6dbcc4,0xbc16bd7d,0x3d46bd22,0x3d713cac,
0x3d6dbcc4,0x3d2c3d3e,0xbcf13d62,0xbd7dbc16,0xbc48bd7b,0x3d5cbd04,0x3d463d22,0xbcac3d71,0xbd353d35,0xbd67bcdb,0x3bc9bd7f,0x3d78bc79,0x3d0e3d55,0xbd183d4e,0xbd75bc95,0xbb49bd80,
0x3cc4bd6d,0x3d803b49,0x3c953d75,0xbd4e3d18,0xbd55bd0e,0x3c79bd78,0x3d7fbbc9,0x3cdb3d67,0x3d80,0xbd713cac,0xbd22bd46,0x3d04bd5c,0x3d7b3c48,0x3c163d7d,0xbd623cf1,0xbd3ebd2c,
0xbd55bd0e,0x3cdbbd67,0x3d753c95,0xbc163d7d,0xbcc4bd6d,0x3d5cbd04,0x3d223d46,0xbd2c3d3e,0x3c48bd7b,0x3d803b49,0x3bc93d7f,0xbd783c79,0x3d35bd35,0x3d4e3d18,0xbcf13d62,0xbd71bcac,
0x3d7bbc48,0x3cac3d71,0xbd623cf1,0xbd18bd4e,0x3d6d3cc4,0xbc793d78,0xbd7fbbc9,0xbb49bd80,0x3d0e3d55,0xbd3e3d2c,0xbd46bd22,0x3d04bd5c,0x3d80,0xbd7d3c16,0xbc95bd75,0x3d67bcdb,
0xbd800000,0xbd80bb49,0xbd7fbbc9,0xbd7dbc16,0xbd7bbc48,0xbd78bc79,0xbd75bc95,0xbd71bcac,0xbd6dbcc4,0xbd67bcdb,0xbd62bcf1,0xbd5cbd04,0xbd55bd0e,0xbd4ebd18,0xbd46bd22,0xbd3ebd2c,
0xbd35bd35,0xbd2cbd3e,0xbd22bd46,0xbd18bd4e,0xbd0ebd55,0xbd04bd5c,0xbcf1bd62,0xbcdbbd67,0xbcc4bd6d,0xbcacbd71,0xbc95bd75,0xbc79bd78,0xbc48bd7b,0xbc16bd7d,0xbbc9bd7f,0xbb49bd80,
0xbd0ebd55,0xbcacbd71,0xbbc9bd7f,0x3c16bd7d,0xbd800000,0xbd78bc79,0xbd62bcf1,0xbd3ebd2c,0x3d7bbc48,0x3d803b49,0x3d753c95,0x3d5c3d04,0x3cc4bd6d,0x3d18bd4e,0x3d46bd22,0x3d67bcdb,
0xbc483d7b,0xbcdb3d67,0xbd223d46,0xbd4e3d18,0x3d353d35,0x3d043d5c,0x3c953d75,0x3b493d80,0xbd55bd0e,0xbd2cbd3e,0xbcf1bd62,0xbc79bd78,0xbd6d3cc4,0xbd7d3c16,0xbd7fbbc9,0xbd71bcac,
0x3d6d3cc4,0x3d2c3d3e,0x3c953d75,0xbc163d7d,0xbd0e3d55,0xbd5c3d04,0xbd7f3bc9,0xbd71bcac,0xbd800000,0xbd67bcdb,0xbd22bd46,0xbc79bd78,0x3c48bd7b,0x3d18bd4e,0x3d62bcf1,0x3d80bb49,
0x3cc43d6d,0xbb493d80,0xbcf13d62,0xbd4e3d18,0xbd7b3c48,0xbd78bc79,0xbd46bd22,0xbcdbbd67,0xbd35bd35,0xbcacbd71,0x3bc9bd7f,0x3d04bd5c,0x3d55bd0e,0x3d7dbc16,0x3d753c95,0x3d3e3d2c,
0xbc48bd7b,0x3cdbbd67,0x3d62bcf1,0x3d7d3c16,0xbcc43d6d,0xbd5c3d04,0xbd7fbbc9,0xbd3ebd2c,0x3d55bd0e,0x3d803b49,0x3d463d22,0x3c793d78,0xbd800000,0xbd4ebd18,0xbc95bd75,0x3cacbd71,
0xbd0e3d55,0xbd713cac,0xbd75bc95,0xbd18bd4e,0x3d6dbcc4,0x3d783c79,0x3d223d46,0x3b493d80,0xbd7bbc48,0xbd2cbd3e,0xbbc9bd7f,0x3d04bd5c,0x3d353d35,0x3c163d7d,0xbcf13d62,0xbd673cdb,
0xbd35bd35,0x3b49bd80,0x3d46bd22,0x3d7d3c16,0x3d0e3d55,0xbc793d78,0xbd623cf1,0xbd71bcac,0xbcc4bd6d,0x3cdbbd67,0x3d75bc95,0x3d5c3d04,0x3c483d7b,0xbd183d4e,0xbd7f3bc9,0xbd3ebd2c,
0xbd800000,0xbd2cbd3e,0x3bc9bd7f,0x3d4ebd18,0x3d7b3c48,0x3d043d5c,0xbc953d75,0xbd673cdb,0xbd6dbcc4,0xbcacbd71,0x3cf1bd62,0x3d78bc79,0x3d553d0e,0x3c163d7d,0xbd223d46,0xbd803b49,
0x3c48bd7b,0x3d71bcac,0x3d463d22,0xbc163d7d,0x3d353d35,0xbc793d78,0xbd753c95,0xbd3ebd2c,0x3d553d0e,0xbb493d80,0xbd623cf1,0xbd5cbd04,0xbd6d3cc4,0xbd4ebd18,0x3bc9bd7f,0x3d67bcdb,
0x3d0e3d55,0xbcdb3d67,0xbd7f3bc9,0xbd18bd4e,0xbd800000,0xbd04bd5c,0x3cf1bd62,0x3d80bb49,0xbd7b3c48,0xbd2cbd3e,0x3c95bd75,0x3d78bc79,0x3cc4bd6d,0x3d7dbc16,0x3d223d46,0xbcac3d71,
0x3cc43d6d,0xbd3e3d2c,0xbd62bcf1,0x3c16bd7d,0x3d7bbc48,0x3d043d5c,0xbd223d46,0xbd71bcac,0xbd35bd35,0x3cdbbd67,0x3d7f3bc9,0x3c793d78,0xbd553d0e,0xbd4ebd18,0x3c95bd75,0x3d80bb49,
0x3d6d3cc4,0xbb493d80,0xbd753c95,0xbd18bd4e,0x3d0ebd55,0x3d783c79,0x3bc93d7f,0xbd673cdb,0xbd800000,0xbcacbd71,0x3d46bd22,0x3d5c3d04,0xbc483d7b,0xbd7d3c16,0xbcf1bd62,0x3d2cbd3e,
0x3d0ebd55,0x3d673cdb,0xbc953d75,0xbd7dbc16,0x3d6dbcc4,0x3d043d5c,0xbd463d22,0xbd3ebd2c,0x3d7b3c48,0xbb493d80,0xbd7f3bc9,0xbc79bd78,0x3d353d35,0xbd183d4e,0xbd62bcf1,0x3cacbd71,
0x3c483d7b,0xbd713cac,0xbcf1bd62,0x3d4ebd18,0xbcc43d6d,0xbd78bc79,0x3bc9bd7f,0x3d80bb49,0xbd553d0e,0xbd2cbd3e,0x3d22bd46,0x3d5c3d04,0xbd800000,0xbc16bd7d,0x3d75bc95,0x3cdb3d67,
0x3d80,0xbd80bb49,0x3bc9bd7f,0x3d7d3c16,0xbc483d7b,0xbd78bc79,0x3c95bd75,0x3d713cac,0xbcc43d6d,0xbd67bcdb,0x3cf1bd62,0x3d5c3d04,0xbd0e3d55,0xbd4ebd18,0x3d22bd46,0x3d3e3d2c,
0xbd353d35,0xbd2cbd3e,0x3d46bd22,0x3d183d4e,0xbd553d0e,0xbd04bd5c,0x3d62bcf1,0x3cdb3d67,0xbd6d3cc4,0xbcacbd71,0x3d75bc95,0x3c793d78,0xbd7b3c48,0xbc16bd7d,0x3d7fbbc9,0x3b493d80,
0xbd553d0e,0xbcacbd71,0x3d7fbbc9,0xbc163d7d,0x3d80,0xbd78bc79,0x3cf1bd62,0x3d3e3d2c,0xbc48bd7b,0x3d803b49,0xbc953d75,0xbd5cbd04,0xbd6dbcc4,0x3d18bd4e,0x3d223d46,0xbd673cdb,
0x3d7b3c48,0xbcdb3d67,0xbd46bd22,0x3d4ebd18,0x3d35bd35,0x3d043d5c,0xbd753c95,0xbb49bd80,0xbd0e3d55,0xbd2cbd3e,0x3d62bcf1,0x3c793d78,0x3cc43d6d,0xbd7d3c16,0x3bc9bd7f,0x3d713cac,
0x3cc4bd6d,0x3d2c3d3e,0xbd753c95,0x3c16bd7d,0x3d553d0e,0xbd5c3d04,0xbbc9bd7f,0x3d713cac,0x3d80,0xbd67bcdb,0x3d46bd22,0x3c793d78,0xbd7bbc48,0x3d18bd4e,0x3cf13d62,0xbd803b49,
0x3d6dbcc4,0xbb493d80,0xbd62bcf1,0x3d4ebd18,0x3c483d7b,0xbd78bc79,0x3d22bd46,0x3cdb3d67,0xbd353d35,0xbcacbd71,0x3d7f3bc9,0xbd043d5c,0xbd0ebd55,0x3d7dbc16,0xbc953d75,0xbd3ebd2c,
0xbd7b3c48,0x3cdbbd67,0x3cf13d62,0xbd7dbc16,0x3d6d3cc4,0xbd5c3d04,0x3bc9bd7f,0x3d3e3d2c,0xbd0ebd55,0x3d803b49,0xbd223d46,0xbc79bd78,0x3d80,0xbd4ebd18,0x3d75bc95,0xbcac3d71,
0x3d553d0e,0xbd713cac,0x3c95bd75,0x3d183d4e,0xbcc4bd6d,0x3d783c79,0xbd463d22,0xbb49bd80,0xbc483d7b,0xbd2cbd3e,0x3d7fbbc9,0xbd043d5c,0x3d35bd35,0x3c163d7d,0xbd62bcf1,0x3d67bcdb,
0xbd353d35,0x3b49bd80,0x3d223d46,0xbd7dbc16,0x3d55bd0e,0xbc793d78,0xbcf1bd62,0x3d713cac,0xbd6d3cc4,0x3cdbbd67,0x3c953d75,0xbd5cbd04,0x3d7bbc48,0xbd183d4e,0xbbc9bd7f,0x3d3e3d2c,
0x3d80,0xbd2cbd3e,0x3d7f3bc9,0xbd4e3d18,0x3c48bd7b,0x3d043d5c,0xbd75bc95,0x3d67bcdb,0xbcc43d6d,0xbcacbd71,0x3d623cf1,0xbd783c79,0x3d0ebd55,0x3c163d7d,0xbd46bd22,0x3d80bb49,
0xbd7bbc48,0x3d71bcac,0xbd223d46,0x3c16bd7d,0x3d35bd35,0xbc793d78,0xbc95bd75,0x3d3e3d2c,0x3d0ebd55,0xbb493d80,0xbcf1bd62,0x3d5c3d04,0x3cc43d6d,0xbd4ebd18,0x3d7f3bc9,0xbd673cdb,
0x3d55bd0e,0xbcdb3d67,0xbbc9bd7f,0x3d183d4e,0x3d80,0xbd04bd5c,0x3d623cf1,0xbd803b49,0x3c483d7b,0xbd2cbd3e,0x3d753c95,0xbd783c79,0xbd6dbcc4,0x3d7dbc16,0xbd463d22,0x3cacbd71,
0x3d6dbcc4,0xbd3e3d2c,0x3cf1bd62,0xbc163d7d,0xbc48bd7b,0x3d043d5c,0xbd46bd22,0x3d713cac,0xbd353d35,0x3cdbbd67,0xbbc93d7f,0xbc79bd78,0x3d0e3d55,0xbd4ebd18,0x3d753c95,0xbd803b49,
0x3cc4bd6d,0xbb493d80,0xbc95bd75,0x3d183d4e,0xbd55bd0e,0x3d783c79,0xbd7f3bc9,0x3d67bcdb,0x3d80,0xbcacbd71,0x3d223d46,0xbd5cbd04,0x3d7b3c48,0xbd7d3c16,0x3d62bcf1,0xbd2c3d3e,
0xbd55bd0e,0x3d673cdb,0xbd75bc95,0x3d7d3c16,0xbcc4bd6d,0x3d043d5c,0xbd22bd46,0x3d3e3d2c,0x3c48bd7b,0xbb493d80,0xbbc9bd7f,0x3c793d78,0x3d35bd35,0xbd183d4e,0x3cf1bd62,0xbcac3d71,
0x3d7bbc48,0xbd713cac,0x3d62bcf1,0xbd4e3d18,0x3d6d3cc4,0xbd78bc79,0x3d7f3bc9,0xbd803b49,0x3d0e3d55,0xbd2cbd3e,0x3d463d22,0xbd5cbd04,0x3d80,0xbc16bd7d,0x3c953d75,0xbcdbbd67,
0xbd800000,0x3b49bd80,0x3d7f3bc9,0xbc163d7d,0xbd7bbc48,0x3c79bd78,0x3d753c95,0xbcac3d71,0xbd6dbcc4,0x3cdbbd67,0x3d623cf1,0xbd043d5c,0xbd55bd0e,0x3d18bd4e,0x3d463d22,0xbd2c3d3e,
0xbd35bd35,0x3d3ebd2c,0x3d223d46,0xbd4e3d18,0xbd0ebd55,0x3d5cbd04,0x3cf13d62,0xbd673cdb,0xbcc4bd6d,0x3d71bcac,0x3c953d75,0xbd783c79,0xbc48bd7b,0x3d7dbc16,0x3bc93d7f,0xbd803b49,
0xbd0ebd55,0x3d71bcac,0x3bc93d7f,0xbd7dbc16,0xbd800000,0x3c79bd78,0x3d623cf1,0xbd2c3d3e,0x3d7bbc48,0xbb493d80,0xbd75bc95,0x3d04bd5c,0x3cc4bd6d,0x3d4e3d18,0xbd463d22,0xbcdbbd67,
0xbc483d7b,0xbd67bcdb,0x3d22bd46,0x3d183d4e,0x3d353d35,0xbd5c3d04,0xbc95bd75,0x3d80bb49,0xbd55bd0e,0x3d3ebd2c,0x3cf13d62,0xbd783c79,0xbd6d3cc4,0xbc16bd7d,0x3d7f3bc9,0xbcac3d71,
0x3d6d3cc4,0xbd3e3d2c,0xbc95bd75,0x3d7d3c16,0xbd0e3d55,0xbd04bd5c,0x3d7fbbc9,0xbcac3d71,0xbd800000,0x3cdbbd67,0x3d223d46,0xbd783c79,0x3c48bd7b,0x3d4e3d18,0xbd623cf1,0xbb49bd80,
0x3cc43d6d,0xbd80bb49,0x3cf1bd62,0x3d183d4e,0xbd7b3c48,0x3c79bd78,0x3d463d22,0xbd673cdb,0xbd35bd35,0x3d71bcac,0xbbc93d7f,0xbd5cbd04,0x3d55bd0e,0x3c163d7d,0xbd75bc95,0x3d2cbd3e,
0xbc48bd7b,0x3d673cdb,0xbd623cf1,0x3c16bd7d,0xbcc43d6d,0xbd04bd5c,0x3d7f3bc9,0xbd2c3d3e,0x3d55bd0e,0xbb493d80,0xbd46bd22,0x3d78bc79,0xbd800000,0x3d18bd4e,0x3c953d75,0xbd71bcac,
0xbd0e3d55,0xbcacbd71,0x3d753c95,0xbd4e3d18,0x3d6dbcc4,0xbc793d78,0xbd22bd46,0x3d80bb49,0xbd7bbc48,0x3d3ebd2c,0x3bc93d7f,0xbd5cbd04,0x3d353d35,0xbd7d3c16,0x3cf1bd62,0x3cdb3d67,
0xbd35bd35,0x3d803b49,0xbd463d22,0x3c16bd7d,0x3d0e3d55,0xbd78bc79,0x3d62bcf1,0xbcac3d71,0xbcc4bd6d,0x3d673cdb,0xbd753c95,0x3d04bd5c,0x3c483d7b,0xbd4ebd18,0x3d7fbbc9,0xbd2c3d3e,
0xbd800000,0x3d3ebd2c,0xbbc93d7f,0xbd18bd4e,0x3d7b3c48,0xbd5c3d04,0x3c95bd75,0x3cdb3d67,0xbd6dbcc4,0x3d71bcac,0xbcf13d62,0xbc79bd78,0x3d553d0e,0xbd7d3c16,0x3d22bd46,0x3b493d80,
0x3c48bd7b,0x3cac3d71,0xbd46bd22,0x3d7d3c16,0x3d353d35,0xbd78bc79,0x3d75bc95,0xbd2c3d3e,0x3d553d0e,0xbd80bb49,0x3d62bcf1,0xbd043d5c,0xbd6d3cc4,0x3d18bd4e,0xbbc93d7f,0xbcdbbd67,
0x3d0e3d55,0xbd67bcdb,0x3d7fbbc9,0xbd4e3d18,0xbd800000,0x3d5cbd04,0xbcf13d62,0xbb49bd80,0xbd7b3c48,0x3d3ebd2c,0xbc953d75,0xbc79bd78,0x3cc4bd6d,0x3c163d7d,0xbd22bd46,0x3d713cac,
0x3cc43d6d,0xbd2cbd3e,0x3d623cf1,0xbd7dbc16,0x3d7bbc48,0xbd5c3d04,0x3d22bd46,0xbcac3d71,0xbd35bd35,0x3d673cdb,0xbd7fbbc9,0x3d78bc79,0xbd553d0e,0x3d18bd4e,0xbc953d75,0xbb49bd80,
0x3d6d3cc4,0xbd80bb49,0x3d75bc95,0xbd4e3d18,0x3d0ebd55,0xbc793d78,0xbbc9bd7f,0x3cdb3d67,0xbd800000,0x3d71bcac,0xbd463d22,0x3d04bd5c,0xbc483d7b,0xbc16bd7d,0x3cf13d62,0xbd3ebd2c,
0x3d0ebd55,0xbcdb3d67,0x3c95bd75,0xbc163d7d,0x3d6dbcc4,0xbd5c3d04,0x3d46bd22,0xbd2c3d3e,0x3d7b3c48,0xbd80bb49,0x3d7fbbc9,0xbd783c79,0x3d353d35,0xbd4ebd18,0x3d623cf1,0xbd71bcac,
0x3c483d7b,0xbcacbd71,0x3cf13d62,0xbd18bd4e,0xbcc43d6d,0x3c79bd78,0xbbc93d7f,0xbb49bd80,0xbd553d0e,0x3d3ebd2c,0xbd223d46,0x3d04bd5c,0xbd800000,0x3d7dbc16,0xbd753c95,0x3d67bcdb,
0x3d80,0x3b49bd80,0xbbc93d7f,0x3c16bd7d,0xbc483d7b,0x3c79bd78,0xbc953d75,0x3cacbd71,0xbcc43d6d,0x3cdbbd67,0xbcf13d62,0x3d04bd5c,0xbd0e3d55,0x3d18bd4e,0xbd223d46,0x3d2cbd3e,
0xbd353d35,0x3d3ebd2c,0xbd463d22,0x3d4ebd18,0xbd553d0e,0x3d5cbd04,0xbd623cf1,0x3d67bcdb,0xbd6d3cc4,0x3d71bcac,0xbd753c95,0x3d78bc79,0xbd7b3c48,0x3d7dbc16,0xbd7f3bc9,0x3d80bb49,
0xbd553d0e,0x3d71bcac,0xbd7f3bc9,0x3d7d3c16,0x3d80,0x3c79bd78,0xbcf13d62,0x3d2cbd3e,0xbc48bd7b,0xbb493d80,0x3c95bd75,0xbd043d5c,0xbd6dbcc4,0x3d4e3d18,0xbd22bd46,0x3cdb3d67,
0x3d7b3c48,0xbd67bcdb,0x3d463d22,0xbd18bd4e,0x3d35bd35,0xbd5c3d04,0x3d75bc95,0xbd803b49,0xbd0e3d55,0x3d3ebd2c,0xbd623cf1,0x3d78bc79,0x3cc43d6d,0xbc16bd7d,0xbbc93d7f,0x3cacbd71,
0x3cc4bd6d,0xbd3e3d2c,0x3d75bc95,0xbd7dbc16,0x3d553d0e,0xbd04bd5c,0x3bc93d7f,0x3cacbd71,0x3d80,0x3cdbbd67,0xbd463d22,0x3d78bc79,0xbd7bbc48,0x3d4e3d18,0xbcf1bd62,0x3b493d80,
0x3d6dbcc4,0xbd80bb49,0x3d623cf1,0xbd18bd4e,0x3c483d7b,0x3c79bd78,0xbd223d46,0x3d67bcdb,0xbd353d35,0x3d71bcac,0xbd7fbbc9,0x3d5c3d04,0xbd0ebd55,0x3c163d7d,0x3c95bd75,0xbd2c3d3e,
0xbd7b3c48,0x3d673cdb,0xbcf1bd62,0xbc163d7d,0x3d6d3cc4,0xbd04bd5c,0xbbc93d7f,0x3d2cbd3e,0xbd0ebd55,0xbb493d80,0x3d22bd46,0xbd783c79,0x3d80,0x3d18bd4e,0xbd753c95,0x3d713cac,
0x3d553d0e,0xbcacbd71,0xbc953d75,0x3d4ebd18,0xbcc4bd6d,0xbc793d78,0x3d46bd22,0xbd803b49,0xbc483d7b,0x3d3ebd2c,0xbd7f3bc9,0x3d5c3d04,0x3d35bd35,0xbd7d3c16,0x3d623cf1,0xbcdbbd67,
0xbd353d35,0x3d803b49,0xbd22bd46,0xbc163d7d,0x3d55bd0e,0xbd78bc79,0x3cf13d62,0x3cacbd71,0xbd6d3cc4,0x3d673cdb,0xbc95bd75,0xbd043d5c,0x3d7bbc48,0xbd4ebd18,0x3bc93d7f,0x3d2cbd3e,
0x3d80,0x3d3ebd2c,0xbd7fbbc9,0x3d183d4e,0x3c48bd7b,0xbd5c3d04,0x3d753c95,0xbcdbbd67,0xbcc43d6d,0x3d71bcac,0xbd62bcf1,0x3c793d78,0x3d0ebd55,0xbd7d3c16,0x3d463d22,0xbb49bd80,
0xbd7bbc48,0x3cac3d71,0x3d22bd46,0xbd7dbc16,0x3d35bd35,0xbd78bc79,0x3c953d75,0x3d2cbd3e,0x3d0ebd55,0xbd80bb49,0x3cf13d62,0x3d04bd5c,0x3cc43d6d,0x3d18bd4e,0xbd7fbbc9,0x3cdb3d67,
0x3d55bd0e,0xbd67bcdb,0x3bc93d7f,0x3d4ebd18,0x3d80,0x3d5cbd04,0xbd62bcf1,0x3b493d80,0x3c483d7b,0x3d3ebd2c,0xbd75bc95,0x3c793d78,0xbd6dbcc4,0x3c163d7d,0x3d46bd22,0xbd71bcac,
0x3d6dbcc4,0xbd2cbd3e,0xbcf13d62,0x3d7d3c16,0xbc48bd7b,0xbd5c3d04,0x3d463d22,0x3cacbd71,0xbd353d35,0x3d673cdb,0x3bc9bd7f,0xbd783c79,0x3d0e3d55,0x3d18bd4e,0xbd75bc95,0x3b493d80,
0x3cc4bd6d,0xbd80bb49,0x3c953d75,0x3d4ebd18,0xbd55bd0e,0xbc793d78,0x3d7fbbc9,0xbcdbbd67,0x3d80,0x3d71bcac,0xbd22bd46,0xbd043d5c,0x3d7b3c48,0xbc16bd7d,0xbd623cf1,0x3d3e3d2c,
0xbd55bd0e,0xbcdb3d67,0x3d753c95,0x3c16bd7d,0xbcc4bd6d,0xbd5c3d04,0x3d223d46,0x3d2cbd3e,0x3c48bd7b,0xbd80bb49,0x3bc93d7f,0x3d78bc79,0x3d35bd35,0xbd4ebd18,0xbcf13d62,0x3d713cac,
0x3d7bbc48,0xbcacbd71,0xbd623cf1,0x3d183d4e,0x3d6d3cc4,0x3c79bd78,0xbd7fbbc9,0x3b493d80,0x3d0e3d55,0x3d3ebd2c,0xbd46bd22,0xbd043d5c,0x3d80,0x3d7dbc16,0xbc95bd75,0xbd673cdb,
0xbd800000,0x3d803b49,0xbd7fbbc9,0x3d7d3c16,0xbd7bbc48,0x3d783c79,0xbd75bc95,0x3d713cac,0xbd6dbcc4,0x3d673cdb,0xbd62bcf1,0x3d5c3d04,0xbd55bd0e,0x3d4e3d18,0xbd46bd22,0x3d3e3d2c,
0xbd35bd35,0x3d2c3d3e,0xbd22bd46,0x3d183d4e,0xbd0ebd55,0x3d043d5c,0xbcf1bd62,0x3cdb3d67,0xbcc4bd6d,0x3cac3d71,0xbc95bd75,0x3c793d78,0xbc48bd7b,0x3c163d7d,0xbbc9bd7f,0x3b493d80,
0xbd0ebd55,0x3cac3d71,0xbbc9bd7f,0xbc163d7d,0xbd800000,0x3d783c79,0xbd62bcf1,0x3d3e3d2c,0x3d7bbc48,0xbd80bb49,0x3d753c95,0xbd5cbd04,0x3cc4bd6d,0xbd183d4e,0x3d46bd22,0xbd673cdb,
0xbc483d7b,0x3cdbbd67,0xbd223d46,0x3d4ebd18,0x3d353d35,0xbd04bd5c,0x3c953d75,0xbb49bd80,0xbd55bd0e,0x3d2c3d3e,0xbcf1bd62,0x3c793d78,0xbd6d3cc4,0x3d7dbc16,0xbd7fbbc9,0x3d713cac,
0x3d6d3cc4,0xbd2cbd3e,0x3c953d75,0x3c16bd7d,0xbd0e3d55,0x3d5cbd04,0xbd7f3bc9,0x3d713cac,0xbd800000,0x3d673cdb,0xbd22bd46,0x3c793d78,0x3c48bd7b,0xbd183d4e,0x3d62bcf1,0xbd803b49,
0x3cc43d6d,0x3b49bd80,0xbcf13d62,0x3d4ebd18,0xbd7b3c48,0x3d783c79,0xbd46bd22,0x3cdb3d67,0xbd35bd35,0x3cac3d71,0x3bc9bd7f,0xbd043d5c,0x3d55bd0e,0xbd7d3c16,0x3d753c95,0xbd3ebd2c,
0xbc48bd7b,0xbcdb3d67,0x3d62bcf1,0xbd7dbc16,0xbcc43d6d,0x3d5cbd04,0xbd7fbbc9,0x3d3e3d2c,0x3d55bd0e,0xbd80bb49,0x3d463d22,0xbc79bd78,0xbd800000,0x3d4e3d18,0xbc95bd75,0xbcac3d71,
0xbd0e3d55,0x3d71bcac,0xbd75bc95,0x3d183d4e,0x3d6dbcc4,0xbd78bc79,0x3d223d46,0xbb49bd80,0xbd7bbc48,0x3d2c3d3e,0xbbc9bd7f,0xbd043d5c,0x3d353d35,0xbc16bd7d,0xbcf13d62,0x3d67bcdb,
0xbd35bd35,0xbb493d80,0x3d46bd22,0xbd7dbc16,0x3d0e3d55,0x3c79bd78,0xbd623cf1,0x3d713cac,0xbcc4bd6d,0xbcdb3d67,0x3d75bc95,0xbd5cbd04,0x3c483d7b,0x3d18bd4e,0xbd7f3bc9,0x3d3e3d2c,
0xbd800000,0x3d2c3d3e,0x3bc9bd7f,0xbd4e3d18,0x3d7b3c48,0xbd04bd5c,0xbc953d75,0x3d67bcdb,0xbd6dbcc4,0x3cac3d71,0x3cf1bd62,0xbd783c79,0x3d553d0e,0xbc16bd7d,0xbd223d46,0x3d80bb49,
0x3c48bd7b,0xbd713cac,0x3d463d22,0x3c16bd7d,0x3d353d35,0x3c79bd78,0xbd753c95,0x3d3e3d2c,0x3d553d0e,0x3b49bd80,0xbd623cf1,0x3d5c3d04,0xbd6d3cc4,0x3d4e3d18,0x3bc9bd7f,0xbd673cdb,
0x3d0e3d55,0x3cdbbd67,0xbd7f3bc9,0x3d183d4e,0xbd800000,0x3d043d5c,0x3cf1bd62,0xbd803b49,0xbd7b3c48,0x3d2c3d3e,0x3c95bd75,0xbd783c79,0x3cc4bd6d,0xbd7d3c16,0x3d223d46,0x3cacbd71,
0x3cc43d6d,0x3d3ebd2c,0xbd62bcf1,0xbc163d7d,0x3d7bbc48,0xbd04bd5c,0xbd223d46,0x3d713cac,0xbd35bd35,0xbcdb3d67,0x3d7f3bc9,0xbc79bd78,0xbd553d0e,0x3d4e3d18,0x3c95bd75,0xbd803b49,
0x3d6d3cc4,0x3b49bd80,0xbd753c95,0x3d183d4e,0x3d0ebd55,0xbd78bc79,0x3bc93d7f,0x3d67bcdb,0xbd800000,0x3cac3d71,0x3d46bd22,0xbd5cbd04,0xbc483d7b,0x3d7dbc16,0xbcf1bd62,0xbd2c3d3e,
0x3d0ebd55,0xbd67bcdb,0xbc953d75,0x3d7d3c16,0x3d6dbcc4,0xbd04bd5c,0xbd463d22,0x3d3e3d2c,0x3d7b3c48,0x3b49bd80,0xbd7f3bc9,0x3c793d78,0x3d353d35,0x3d18bd4e,0xbd62bcf1,0xbcac3d71,
0x3c483d7b,0x3d71bcac,0xbcf1bd62,0xbd4e3d18,0xbcc43d6d,0x3d783c79,0x3bc9bd7f,0xbd803b49,0xbd553d0e,0x3d2c3d3e,0x3d22bd46,0xbd5cbd04,0xbd800000,0x3c163d7d,0x3d75bc95,0xbcdbbd67,
0x3d80,0x3d803b49,0x3bc9bd7f,0xbd7dbc16,0xbc483d7b,0x3d783c79,0x3c95bd75,0xbd71bcac,0xbcc43d6d,0x3d673cdb,0x3cf1bd62,0xbd5cbd04,0xbd0e3d55,0x3d4e3d18,0x3d22bd46,0xbd3ebd2c,
0xbd353d35,0x3d2c3d3e,0x3d46bd22,0xbd18bd4e,0xbd553d0e,0x3d043d5c,0x3d62bcf1,0xbcdbbd67,0xbd6d3cc4,0x3cac3d71,0x3d75bc95,0xbc79bd78,0xbd7b3c48,0x3c163d7d,0x3d7fbbc9,0xbb49bd80,
0xbd553d0e,0x3cac3d71,0x3d7fbbc9,0x3c16bd7d,0x3d80,0x3d783c79,0x3cf1bd62,0xbd3ebd2c,0xbc48bd7b,0xbd80bb49,0xbc953d75,0x3d5c3d04,0xbd6dbcc4,0xbd183d4e,0x3d223d46,0x3d67bcdb,
0x3d7b3c48,0x3cdbbd67,0xbd46bd22,0xbd4e3d18,0x3d35bd35,0xbd04bd5c,0xbd753c95,0x3b493d80,0xbd0e3d55,0x3d2c3d3e,0x3d62bcf1,0xbc79bd78,0x3cc43d6d,0x3d7dbc16,0x3bc9bd7f,0xbd71bcac,
0x3cc4bd6d,0xbd2cbd3e,0xbd753c95,0xbc163d7d,0x3d553d0e,0x3d5cbd04,0xbbc9bd7f,0xbd71bcac,0x3d80,0x3d673cdb,0x3d46bd22,0xbc79bd78,0xbd7bbc48,0xbd183d4e,0x3cf13d62,0x3d80bb49,
0x3d6dbcc4,0x3b49bd80,0xbd62bcf1,0xbd4e3d18,0x3c483d7b,0x3d783c79,0x3d22bd46,0xbcdbbd67,0xbd353d35,0x3cac3d71,0x3d7f3bc9,0x3d04bd5c,0xbd0ebd55,0xbd7d3c16,0xbc953d75,0x3d3e3d2c,
0xbd7b3c48,0xbcdb3d67,0x3cf13d62,0x3d7d3c16,0x3d6d3cc4,0x3d5cbd04,0x3bc9bd7f,0xbd3ebd2c,0xbd0ebd55,0xbd80bb49,0xbd223d46,0x3c793d78,0x3d80,0x3d4e3d18,0x3d75bc95,0x3cacbd71,
0x3d553d0e,0x3d71bcac,0x3c95bd75,0xbd18bd4e,0xbcc4bd6d,0xbd78bc79,0xbd463d22,0x3b493d80,0xbc483d7b,0x3d2c3d3e,0x3d7fbbc9,0x3d04bd5c,0x3d35bd35,0xbc16bd7d,0xbd62bcf1,0xbd673cdb,
0xbd353d35,0xbb493d80,0x3d223d46,0x3d7d3c16,0x3d55bd0e,0x3c79bd78,0xbcf1bd62,0xbd71bcac,0xbd6d3cc4,0xbcdb3d67,0x3c953d75,0x3d5c3d04,0x3d7bbc48,0x3d18bd4e,0xbbc9bd7f,0xbd3ebd2c,
0x3d80,0x3d2c3d3e,0x3d7f3bc9,0x3d4ebd18,0x3c48bd7b,0xbd04bd5c,0xbd75bc95,0xbd673cdb,0xbcc43d6d,0x3cac3d71,0x3d623cf1,0x3d78bc79,0x3d0ebd55,0xbc16bd7d,0xbd46bd22,0xbd803b49,
0xbd7bbc48,0xbd713cac,0xbd223d46,0xbc163d7d,0x3d35bd35,0x3c79bd78,0xbc95bd75,0xbd3ebd2c,0x3d0ebd55,0x3b49bd80,0xbcf1bd62,0xbd5cbd04,0x3cc43d6d,0x3d4e3d18,0x3d7f3bc9,0x3d67bcdb,
0x3d55bd0e,0x3cdbbd67,0xbbc9bd7f,0xbd18bd4e,0x3d80,0x3d043d5c,0x3d623cf1,0x3d80bb49,0x3c483d7b,0x3d2c3d3e,0x3d753c95,0x3d78bc79,0xbd6dbcc4,0xbd7d3c16,0xbd463d22,0xbcac3d71,
0x3d6dbcc4,0x3d3ebd2c,0x3cf1bd62,0x3c16bd7d,0xbc48bd7b,0xbd04bd5c,0xbd46bd22,0xbd71bcac,0xbd353d35,0xbcdb3d67,0xbbc93d7f,0x3c793d78,0x3d0e3d55,0x3d4e3d18,0x3d753c95,0x3d80bb49,
0x3cc4bd6d,0x3b49bd80,0xbc95bd75,0xbd18bd4e,0xbd55bd0e,0xbd78bc79,0xbd7f3bc9,0xbd673cdb,0x3d80,0x3cac3d71,0x3d223d46,0x3d5c3d04,0x3d7b3c48,0x3d7dbc16,0x3d62bcf1,0x3d2cbd3e,
0xbd55bd0e,0xbd67bcdb,0xbd75bc95,0xbd7dbc16,0xbcc4bd6d,0xbd04bd5c,0xbd22bd46,0xbd3ebd2c,0x3c48bd7b,0x3b49bd80,0xbbc9bd7f,0xbc79bd78,0x3d35bd35,0x3d18bd4e,0x3cf1bd62,0x3cacbd71,
0x3d7bbc48,0x3d71bcac,0x3d62bcf1,0x3d4ebd18,0x3d6d3cc4,0x3d783c79,0x3d7f3bc9,0x3d80bb49,0x3d0e3d55,0x3d2c3d3e,0x3d463d22,0x3d5c3d04,0x3d80,0x3c163d7d,0x3c953d75,0x3cdb3d67,
0xbd800000,0xbb493d80,0x3d7f3bc9,0x3c16bd7d,0xbd7bbc48,0xbc793d78,0x3d753c95,0x3cacbd71,0xbd6dbcc4,0xbcdb3d67,0x3d623cf1,0x3d04bd5c,0xbd55bd0e,0xbd183d4e,0x3d463d22,0x3d2cbd3e,
0xbd35bd35,0xbd3e3d2c,0x3d223d46,0x3d4ebd18,0xbd0ebd55,0xbd5c3d04,0x3cf13d62,0x3d67bcdb,0xbcc4bd6d,0xbd713cac,0x3c953d75,0x3d78bc79,0xbc48bd7b,0xbd7d3c16,0x3bc93d7f,0x3d80bb49,
0xbd0ebd55,0xbd713cac,0x3bc93d7f,0x3d7d3c16,0xbd800000,0xbc793d78,0x3d623cf1,0x3d2cbd3e,0x3d7bbc48,0x3b49bd80,0xbd75bc95,0xbd043d5c,0x3cc4bd6d,0xbd4ebd18,0xbd463d22,0x3cdb3d67,
0xbc483d7b,0x3d673cdb,0x3d22bd46,0xbd18bd4e,0x3d353d35,0x3d5cbd04,0xbc95bd75,0xbd803b49,0xbd55bd0e,0xbd3e3d2c,0x3cf13d62,0x3d78bc79,0xbd6d3cc4,0x3c163d7d,0x3d7f3bc9,0x3cacbd71,
0x3d6d3cc4,0x3d3ebd2c,0xbc95bd75,0xbd7dbc16,0xbd0e3d55,0x3d043d5c,0x3d7fbbc9,0x3cacbd71,0xbd800000,0xbcdb3d67,0x3d223d46,0x3d78bc79,0x3c48bd7b,0xbd4ebd18,0xbd623cf1,0x3b493d80,
0x3cc43d6d,0x3d803b49,0x3cf1bd62,0xbd18bd4e,0xbd7b3c48,0xbc793d78,0x3d463d22,0x3d67bcdb,0xbd35bd35,0xbd713cac,0xbbc93d7f,0x3d5c3d04,0x3d55bd0e,0xbc16bd7d,0xbd75bc95,0xbd2c3d3e,
0xbc48bd7b,0xbd67bcdb,0xbd623cf1,0xbc163d7d,0xbcc43d6d,0x3d043d5c,0x3d7f3bc9,0x3d2cbd3e,0x3d55bd0e,0x3b49bd80,0xbd46bd22,0xbd783c79,0xbd800000,0xbd183d4e,0x3c953d75,0x3d713cac,
0xbd0e3d55,0x3cac3d71,0x3d753c95,0x3d4ebd18,0x3d6dbcc4,0x3c79bd78,0xbd22bd46,0xbd803b49,0xbd7bbc48,0xbd3e3d2c,0x3bc93d7f,0x3d5c3d04,0x3d353d35,0x3d7dbc16,0x3cf1bd62,0xbcdbbd67,
0xbd35bd35,0xbd80bb49,0xbd463d22,0xbc163d7d,0x3d0e3d55,0x3d783c79,0x3d62bcf1,0x3cacbd71,0xbcc4bd6d,0xbd67bcdb,0xbd753c95,0xbd043d5c,0x3c483d7b,0x3d4e3d18,0x3d7fbbc9,0x3d2cbd3e,
0xbd800000,0xbd3e3d2c,0xbbc93d7f,0x3d183d4e,0x3d7b3c48,0x3d5cbd04,0x3c95bd75,0xbcdbbd67,0xbd6dbcc4,0xbd713cac,0xbcf13d62,0x3c793d78,0x3d553d0e,0x3d7dbc16,0x3d22bd46,0xbb49bd80,
0x3c48bd7b,0xbcacbd71,0xbd46bd22,0xbd7dbc16,0x3d353d35,0x3d783c79,0x3d75bc95,0x3d2cbd3e,0x3d553d0e,0x3d803b49,0x3d62bcf1,0x3d04bd5c,0xbd6d3cc4,0xbd183d4e,0xbbc93d7f,0x3cdb3d67,
0x3d0e3d55,0x3d673cdb,0x3d7fbbc9,0x3d4ebd18,0xbd800000,0xbd5c3d04,0xbcf13d62,0x3b493d80,0xbd7b3c48,0xbd3e3d2c,0xbc953d75,0x3c793d78,0x3cc4bd6d,0xbc16bd7d,0xbd22bd46,0xbd71bcac,
0x3cc43d6d,0x3d2c3d3e,0x3d623cf1,0x3d7d3c16,0x3d7bbc48,0x3d5cbd04,0x3d22bd46,0x3cacbd71,0xbd35bd35,0xbd67bcdb,0xbd7fbbc9,0xbd783c79,0xbd553d0e,0xbd183d4e,0xbc953d75,0x3b493d80,
0x3d6d3cc4,0x3d803b49,0x3d75bc95,0x3d4ebd18,0x3d0ebd55,0x3c79bd78,0xbbc9bd7f,0xbcdbbd67,0xbd800000,0xbd713cac,0xbd463d22,0xbd043d5c,0xbc483d7b,0x3c163d7d,0x3cf13d62,0x3d3e3d2c,
0x3d0ebd55,0x3cdbbd67,0x3c95bd75,0x3c16bd7d,0x3d6dbcc4,0x3d5cbd04,0x3d46bd22,0x3d2cbd3e,0x3d7b3c48,0x3d803b49,0x3d7fbbc9,0x3d78bc79,0x3d353d35,0x3d4e3d18,0x3d623cf1,0x3d713cac,
0x3c483d7b,0x3cac3d71,0x3cf13d62,0x3d183d4e,0xbcc43d6d,0xbc793d78,0xbbc93d7f,0x3b493d80,0xbd553d0e,0xbd3e3d2c,0xbd223d46,0xbd043d5c,0xbd800000,0xbd7d3c16,0xbd753c95,0xbd673cdb,
0x3d80,0xbbc93d7f,0xbc483d7b,0xbc953d75,0xbcc43d6d,0xbcf13d62,0xbd0e3d55,0xbd223d46,0xbd353d35,0xbd463d22,0xbd553d0e,0xbd623cf1,0xbd6d3cc4,0xbd753c95,0xbd7b3c48,0xbd7f3bc9,
0xbd800000,0xbd7fbbc9,0xbd7bbc48,0xbd75bc95,0xbd6dbcc4,0xbd62bcf1,0xbd55bd0e,0xbd46bd22,0xbd35bd35,0xbd22bd46,0xbd0ebd55,0xbcf1bd62,0xbcc4bd6d,0xbc95bd75,0xbc48bd7b,0xbbc9bd7f,
0xbd6d3cc4,0xbd7f3bc9,0xbd7bbc48,0xbd62bcf1,0x3d80,0xbc953d75,0xbd0e3d55,0xbd463d22,0x3cc4bd6d,0x3d22bd46,0x3d55bd0e,0x3d75bc95,0xbd35bd35,0xbcf1bd62,0xbc48bd7b,0x3bc9bd7f,
0x3cc43d6d,0x3bc93d7f,0xbc483d7b,0xbcf13d62,0x3d800000,0x3d753c95,0x3d553d0e,0x3d223d46,0xbd6dbcc4,0xbd46bd22,0xbd0ebd55,0xbc95bd75,0xbd353d35,0xbd623cf1,0xbd7b3c48,0xbd7fbbc9,
0x3d35bd35,0x3d75bc95,0x3d7b3c48,0x3d463d22,0x3cc43d6d,0xbbc93d7f,0xbd0e3d55,0xbd623cf1,0x3d80,0xbcf13d62,0xbd553d0e,0xbd7f3bc9,0xbd6dbcc4,0xbd22bd46,0xbc48bd7b,0x3c95bd75,
0x3d353d35,0x3c953d75,0xbc483d7b,0xbd223d46,0xbd6d3cc4,0xbd7fbbc9,0xbd55bd0e,0xbcf1bd62,0xbd800000,0xbd62bcf1,0xbd0ebd55,0xbbc9bd7f,0x3cc4bd6d,0x3d46bd22,0x3d7bbc48,0x3d753c95,
0xbd6dbcc4,0xbcf1bd62,0x3c48bd7b,0x3d46bd22,0x3d353d35,0x3bc93d7f,0xbd0e3d55,0xbd753c95,0xbcc4bd6d,0x3c95bd75,0x3d55bd0e,0x3d7f3bc9,0x3d80,0xbd223d46,0xbd7b3c48,0xbd62bcf1,
0xbcc43d6d,0xbd623cf1,0xbd7bbc48,0xbd22bd46,0x3d35bd35,0x3d7fbbc9,0x3d553d0e,0x3c953d75,0xbd6d3cc4,0xbd75bc95,0xbd0ebd55,0x3bc9bd7f,0x3d800000,0x3d463d22,0x3c483d7b,0xbcf13d62,
0xbd800000,0xbd22bd46,0x3c48bd7b,0x3d62bcf1,0x3d6d3cc4,0x3c953d75,0xbd0e3d55,0xbd7f3bc9,0xbd35bd35,0x3bc9bd7f,0x3d55bd0e,0x3d753c95,0x3cc43d6d,0xbcf13d62,0xbd7b3c48,0xbd46bd22,
0x3d80,0xbd463d22,0xbd7bbc48,0xbcf1bd62,0x3cc4bd6d,0x3d75bc95,0x3d553d0e,0x3bc93d7f,0xbd353d35,0xbd7fbbc9,0xbd0ebd55,0x3c95bd75,0x3d6dbcc4,0x3d623cf1,0x3c483d7b,0xbd223d46,
0xbcc4bd6d,0x3d22bd46,0x3d7b3c48,0x3c953d75,0x3d800000,0x3cf13d62,0xbd0e3d55,0xbd7fbbc9,0x3d6d3cc4,0x3bc93d7f,0xbd553d0e,0xbd62bcf1,0xbd353d35,0xbd75bc95,0xbc48bd7b,0x3d46bd22,
0x3d6dbcc4,0x3d463d22,0xbc483d7b,0xbd753c95,0x3d80,0xbd623cf1,0xbd55bd0e,0x3bc9bd7f,0xbcc43d6d,0xbd7f3bc9,0xbd0ebd55,0x3cf1bd62,0xbd35bd35,0x3c95bd75,0x3d7bbc48,0x3d223d46,
0x3d353d35,0xbcf13d62,0xbd7bbc48,0xbbc9bd7f,0x3d6dbcc4,0x3d223d46,0xbd0e3d55,0xbd75bc95,0xbd800000,0xbc95bd75,0x3d55bd0e,0x3d463d22,0xbcc43d6d,0xbd7fbbc9,0xbc48bd7b,0x3d62bcf1,
0x3d35bd35,0x3d623cf1,0xbc483d7b,0xbd7f3bc9,0xbcc4bd6d,0x3d46bd22,0x3d553d0e,0xbc953d75,0x3d80,0xbd753c95,0xbd0ebd55,0x3d22bd46,0x3d6d3cc4,0xbbc93d7f,0xbd7b3c48,0xbcf1bd62,
0x3cc4bd6d,0x3d753c95,0xbc483d7b,0xbd7fbbc9,0x3d35bd35,0x3d463d22,0xbd0e3d55,0xbd62bcf1,0x3d6dbcc4,0x3cf13d62,0xbd553d0e,0xbd22bd46,0x3d800000,0x3bc93d7f,0xbd7b3c48,0xbc95bd75,
0x3d6d3cc4,0xbc953d75,0xbd7bbc48,0x3bc9bd7f,0x3d353d35,0xbd223d46,0xbd55bd0e,0x3cf1bd62,0x3cc43d6d,0xbd623cf1,0xbd0ebd55,0x3d46bd22,0x3d80,0xbd7f3bc9,0xbc48bd7b,0x3d75bc95,
0xbd800000,0xbd7fbbc9,0xbd7bbc48,0xbd75bc95,0xbd6dbcc4,0xbd62bcf1,0xbd55bd0e,0xbd46bd22,0xbd35bd35,0xbd22bd46,0xbd0ebd55,0xbcf1bd62,0xbcc4bd6d,0xbc95bd75,0xbc48bd7b,0xbbc9bd7f,
0x8000bd80,0x3bc9bd7f,0x3c48bd7b,0x3c95bd75,0x3cc4bd6d,0x3cf1bd62,0x3d0ebd55,0x3d22bd46,0x3d35bd35,0x3d46bd22,0x3d55bd0e,0x3d62bcf1,0x3d6dbcc4,0x3d75bc95,0x3d7bbc48,0x3d7fbbc9,
0xbcc4bd6d,0xbbc9bd7f,0x3c48bd7b,0x3cf1bd62,0xbd800000,0xbd75bc95,0xbd55bd0e,0xbd22bd46,0x3d6d3cc4,0x3d463d22,0x3d0e3d55,0x3c953d75,0x3d35bd35,0x3d62bcf1,0x3d7bbc48,0x3d7f3bc9,
0xbd6d3cc4,0xbd7f3bc9,0xbd7bbc48,0xbd62bcf1,0x80003d80,0xbc953d75,0xbd0e3d55,0xbd463d22,0x3cc4bd6d,0x3d22bd46,0x3d55bd0e,0x3d75bc95,0xbd35bd35,0xbcf1bd62,0xbc48bd7b,0x3bc9bd7f,
0x3d353d35,0x3c953d75,0xbc483d7b,0xbd223d46,0xbd6d3cc4,0xbd7fbbc9,0xbd55bd0e,0xbcf1bd62,0xbd800000,0xbd62bcf1,0xbd0ebd55,0xbbc9bd7f,0x3cc4bd6d,0x3d46bd22,0x3d7bbc48,0x3d753c95,
0xbd353d35,0xbd753c95,0xbd7bbc48,0xbd46bd22,0xbcc4bd6d,0x3bc9bd7f,0x3d0ebd55,0x3d62bcf1,0x8000bd80,0x3cf1bd62,0x3d55bd0e,0x3d7fbbc9,0x3d6d3cc4,0x3d223d46,0x3c483d7b,0xbc953d75,
0x3cc4bd6d,0x3d62bcf1,0x3d7b3c48,0x3d223d46,0xbd353d35,0xbd7f3bc9,0xbd55bd0e,0xbc95bd75,0x3d6dbcc4,0x3d753c95,0x3d0e3d55,0xbbc93d7f,0xbd800000,0xbd46bd22,0xbc48bd7b,0x3cf1bd62,
0xbd6dbcc4,0xbcf1bd62,0x3c48bd7b,0x3d46bd22,0x3d353d35,0x3bc93d7f,0xbd0e3d55,0xbd753c95,0xbcc4bd6d,0x3c95bd75,0x3d55bd0e,0x3d7f3bc9,0x80003d80,0xbd223d46,0xbd7b3c48,0xbd62bcf1,
0x8000bd80,0x3d46bd22,0x3d7b3c48,0x3cf13d62,0xbcc43d6d,0xbd753c95,0xbd55bd0e,0xbbc9bd7f,0x3d35bd35,0x3d7f3bc9,0x3d0e3d55,0xbc953d75,0xbd6d3cc4,0xbd62bcf1,0xbc48bd7b,0x3d22bd46,
0xbd800000,0xbd22bd46,0x3c48bd7b,0x3d62bcf1,0x3d6d3cc4,0x3c953d75,0xbd0e3d55,0xbd7f3bc9,0xbd35bd35,0x3bc9bd7f,0x3d55bd0e,0x3d753c95,0x3cc43d6d,0xbcf13d62,0xbd7b3c48,0xbd46bd22,
0x3d6dbcc4,0x3d463d22,0xbc483d7b,0xbd753c95,0x80003d80,0xbd623cf1,0xbd55bd0e,0x3bc9bd7f,0xbcc43d6d,0xbd7f3bc9,0xbd0ebd55,0x3cf1bd62,0xbd35bd35,0x3c95bd75,0x3d7bbc48,0x3d223d46,
0x3cc43d6d,0xbd223d46,0xbd7bbc48,0xbc95bd75,0xbd800000,0xbcf1bd62,0x3d0ebd55,0x3d7f3bc9,0xbd6dbcc4,0xbbc9bd7f,0x3d55bd0e,0x3d623cf1,0x3d35bd35,0x3d753c95,0x3c483d7b,0xbd463d22,
0xbd353d35,0xbd62bcf1,0x3c48bd7b,0x3d7fbbc9,0x3cc43d6d,0xbd463d22,0xbd55bd0e,0x3c95bd75,0x8000bd80,0x3d75bc95,0x3d0e3d55,0xbd223d46,0xbd6dbcc4,0x3bc9bd7f,0x3d7bbc48,0x3cf13d62,
0x3d353d35,0xbcf13d62,0xbd7bbc48,0xbbc9bd7f,0x3d6dbcc4,0x3d223d46,0xbd0e3d55,0xbd75bc95,0xbd800000,0xbc95bd75,0x3d55bd0e,0x3d463d22,0xbcc43d6d,0xbd7fbbc9,0xbc48bd7b,0x3d62bcf1,
0x3d6d3cc4,0xbc953d75,0xbd7bbc48,0x3bc9bd7f,0x3d353d35,0xbd223d46,0xbd55bd0e,0x3cf1bd62,0x3cc43d6d,0xbd623cf1,0xbd0ebd55,0x3d46bd22,0x80003d80,0xbd7f3bc9,0xbc48bd7b,0x3d75bc95,
0xbcc43d6d,0xbd75bc95,0x3c48bd7b,0x3d7f3bc9,0xbd353d35,0xbd46bd22,0x3d0ebd55,0x3d623cf1,0xbd6d3cc4,0xbcf1bd62,0x3d55bd0e,0x3d223d46,0xbd800000,0xbbc9bd7f,0x3d7bbc48,0x3c953d75,
0x3d80,0xbd7fbbc9,0x3c48bd7b,0x3d753c95,0xbcc43d6d,0xbd62bcf1,0x3d0ebd55,0x3d463d22,0xbd353d35,0xbd22bd46,0x3d55bd0e,0x3cf13d62,0xbd6d3cc4,0xbc95bd75,0x3d7bbc48,0x3bc93d7f,
0xbd800000,0x3bc9bd7f,0x3d7b3c48,0xbc953d75,0xbd6dbcc4,0x3cf1bd62,0x3d553d0e,0xbd223d46,0xbd35bd35,0x3d46bd22,0x3d0e3d55,0xbd623cf1,0xbcc4bd6d,0x3d75bc95,0x3c483d7b,0xbd7f3bc9,
0xbd6d3cc4,0xbbc9bd7f,0x3d7b3c48,0xbcf13d62,0x3d80,0xbd75bc95,0x3d0ebd55,0x3d223d46,0x3cc4bd6d,0x3d463d22,0xbd553d0e,0xbc95bd75,0xbd35bd35,0x3d62bcf1,0x3c483d7b,0xbd7fbbc9,
0x3cc43d6d,0xbd7f3bc9,0x3c48bd7b,0x3d623cf1,0x3d800000,0xbc953d75,0xbd55bd0e,0x3d46bd22,0xbd6dbcc4,0x3d22bd46,0x3d0e3d55,0xbd753c95,0xbd353d35,0xbcf1bd62,0x3d7bbc48,0xbbc93d7f,
0x3d35bd35,0x3c953d75,0xbd7bbc48,0x3d22bd46,0x3cc43d6d,0xbd7fbbc9,0x3d0ebd55,0x3cf13d62,0x3d80,0xbd62bcf1,0x3d55bd0e,0x3bc93d7f,0xbd6dbcc4,0x3d46bd22,0x3c483d7b,0xbd75bc95,
0x3d353d35,0xbd753c95,0x3c48bd7b,0x3d463d22,0xbd6d3cc4,0x3bc9bd7f,0x3d553d0e,0xbd623cf1,0xbd800000,0x3cf1bd62,0x3d0e3d55,0xbd7f3bc9,0x3cc4bd6d,0x3d223d46,0xbd7b3c48,0x3c95bd75,
0xbd6dbcc4,0x3d62bcf1,0xbc483d7b,0xbd22bd46,0x3d353d35,0xbd7f3bc9,0x3d0ebd55,0x3c953d75,0xbcc4bd6d,0x3d753c95,0xbd553d0e,0x3bc9bd7f,0x3d80,0xbd46bd22,0x3d7bbc48,0xbcf13d62,
0xbcc43d6d,0xbcf1bd62,0x3d7b3c48,0xbd463d22,0x3d35bd35,0x3bc93d7f,0xbd55bd0e,0x3d75bc95,0xbd6d3cc4,0x3c95bd75,0x3d0e3d55,0xbd7fbbc9,0x3d800000,0xbd223d46,0xbc48bd7b,0x3d623cf1,
0xbd800000,0x3d46bd22,0xbc483d7b,0xbcf1bd62,0x3d6d3cc4,0xbd753c95,0x3d0ebd55,0x3bc93d7f,0xbd35bd35,0x3d7f3bc9,0xbd553d0e,0x3c95bd75,0x3cc43d6d,0xbd62bcf1,0x3d7bbc48,0xbd223d46,
0x3d80,0xbd22bd46,0x3d7b3c48,0xbd623cf1,0x3cc4bd6d,0x3c953d75,0xbd55bd0e,0x3d7fbbc9,0xbd353d35,0x3bc9bd7f,0x3d0e3d55,0xbd75bc95,0x3d6dbcc4,0xbcf13d62,0xbc48bd7b,0x3d463d22,
0xbcc4bd6d,0x3d463d22,0xbd7bbc48,0x3d75bc95,0x3d800000,0xbd623cf1,0x3d0ebd55,0xbbc93d7f,0x3d6d3cc4,0xbd7f3bc9,0x3d55bd0e,0xbcf13d62,0xbd353d35,0x3c95bd75,0x3c483d7b,0xbd22bd46,
0x3d6dbcc4,0xbd223d46,0x3c48bd7b,0x3c953d75,0x3d80,0xbcf1bd62,0x3d553d0e,0xbd7fbbc9,0xbcc43d6d,0xbbc9bd7f,0x3d0e3d55,0xbd62bcf1,0xbd35bd35,0x3d753c95,0xbd7b3c48,0x3d46bd22,
0x3d353d35,0xbd62bcf1,0x3d7b3c48,0xbd7f3bc9,0x3d6dbcc4,0xbd463d22,0x3d0ebd55,0xbc953d75,0xbd800000,0x3d75bc95,0xbd553d0e,0x3d22bd46,0xbcc43d6d,0x3bc9bd7f,0x3c483d7b,0xbcf1bd62,
0x3d35bd35,0xbcf13d62,0x3c48bd7b,0x3bc93d7f,0xbcc4bd6d,0x3d223d46,0xbd55bd0e,0x3d753c95,0x3d80,0xbc95bd75,0x3d0e3d55,0xbd46bd22,0x3d6d3cc4,0xbd7fbbc9,0x3d7bbc48,0xbd623cf1,
0x3cc4bd6d,0xbc953d75,0x3c48bd7b,0xbbc93d7f,0x3d35bd35,0xbd223d46,0x3d0ebd55,0xbcf13d62,0x3d6dbcc4,0xbd623cf1,0x3d55bd0e,0xbd463d22,0x3d800000,0xbd7f3bc9,0x3d7bbc48,0xbd753c95,
0x3d6d3cc4,0xbd75bc95,0x3d7b3c48,0xbd7fbbc9,0x3d353d35,0xbd46bd22,0x3d553d0e,0xbd62bcf1,0x3cc43d6d,0xbcf1bd62,0x3d0e3d55,0xbd22bd46,0x3d80,0xbbc9bd7f,0x3c483d7b,0xbc95bd75,
0xbd800000,0x3bc9bd7f,0x3d7b3c48,0xbc953d75,0xbd6dbcc4,0x3cf1bd62,0x3d553d0e,0xbd223d46,0xbd35bd35,0x3d46bd22,0x3d0e3d55,0xbd623cf1,0xbcc4bd6d,0x3d75bc95,0x3c483d7b,0xbd7f3bc9,
0x8000bd80,0x3d7f3bc9,0xbc483d7b,0xbd75bc95,0x3cc4bd6d,0x3d623cf1,0xbd0e3d55,0xbd46bd22,0x3d35bd35,0x3d223d46,0xbd553d0e,0xbcf1bd62,0x3d6dbcc4,0x3c953d75,0xbd7b3c48,0xbbc9bd7f,
0xbcc4bd6d,0x3d7fbbc9,0xbc483d7b,0xbd62bcf1,0xbd800000,0x3c95bd75,0x3d553d0e,0xbd463d22,0x3d6d3cc4,0xbd223d46,0xbd0ebd55,0x3d75bc95,0x3d35bd35,0x3cf13d62,0xbd7b3c48,0x3bc9bd7f,
0xbd6d3cc4,0xbbc9bd7f,0x3d7b3c48,0xbcf13d62,0x80003d80,0xbd75bc95,0x3d0ebd55,0x3d223d46,0x3cc4bd6d,0x3d463d22,0xbd553d0e,0xbc95bd75,0xbd35bd35,0x3d62bcf1,0x3c483d7b,0xbd7fbbc9,
0x3d353d35,0xbd753c95,0x3c48bd7b,0x3d463d22,0xbd6d3cc4,0x3bc9bd7f,0x3d553d0e,0xbd623cf1,0xbd800000,0x3cf1bd62,0x3d0e3d55,0xbd7f3bc9,0x3cc4bd6d,0x3d223d46,0xbd7b3c48,0x3c95bd75,
0xbd353d35,0xbc95bd75,0x3d7b3c48,0xbd223d46,0xbcc4bd6d,0x3d7f3bc9,0xbd0e3d55,0xbcf1bd62,0x8000bd80,0x3d623cf1,0xbd553d0e,0xbbc9bd7f,0x3d6d3cc4,0xbd463d22,0xbc48bd7b,0x3d753c95,
0x3cc4bd6d,0x3cf13d62,0xbd7bbc48,0x3d46bd22,0xbd353d35,0xbbc9bd7f,0x3d553d0e,0xbd753c95,0x3d6dbcc4,0xbc953d75,0xbd0ebd55,0x3d7f3bc9,0xbd800000,0x3d22bd46,0x3c483d7b,0xbd62bcf1,
0xbd6dbcc4,0x3d62bcf1,0xbc483d7b,0xbd22bd46,0x3d353d35,0xbd7f3bc9,0x3d0ebd55,0x3c953d75,0xbcc4bd6d,0x3d753c95,0xbd553d0e,0x3bc9bd7f,0x80003d80,0xbd46bd22,0x3d7bbc48,0xbcf13d62,
0x8000bd80,0x3d223d46,0xbd7bbc48,0x3d62bcf1,0xbcc43d6d,0xbc95bd75,0x3d553d0e,0xbd7f3bc9,0x3d35bd35,0xbbc93d7f,0xbd0ebd55,0x3d753c95,0xbd6d3cc4,0x3cf1bd62,0x3c483d7b,0xbd46bd22,
0xbd800000,0x3d46bd22,0xbc483d7b,0xbcf1bd62,0x3d6d3cc4,0xbd753c95,0x3d0ebd55,0x3bc93d7f,0xbd35bd35,0x3d7f3bc9,0xbd553d0e,0x3c95bd75,0x3cc43d6d,0xbd62bcf1,0x3d7bbc48,0xbd223d46,
0x3d6dbcc4,0xbd223d46,0x3c48bd7b,0x3c953d75,0x80003d80,0xbcf1bd62,0x3d553d0e,0xbd7fbbc9,0xbcc43d6d,0xbbc9bd7f,0x3d0e3d55,0xbd62bcf1,0xbd35bd35,0x3d753c95,0xbd7b3c48,0x3d46bd22,
0x3cc43d6d,0xbd46bd22,0x3d7b3c48,0xbd753c95,0xbd800000,0x3d62bcf1,0xbd0e3d55,0x3bc9bd7f,0xbd6dbcc4,0x3d7fbbc9,0xbd553d0e,0x3cf1bd62,0x3d35bd35,0xbc953d75,0xbc48bd7b,0x3d223d46,
0xbd353d35,0x3cf1bd62,0xbc483d7b,0xbbc9bd7f,0x3cc43d6d,0xbd22bd46,0x3d553d0e,0xbd75bc95,0x8000bd80,0x3c953d75,0xbd0ebd55,0x3d463d22,0xbd6dbcc4,0x3d7f3bc9,0xbd7b3c48,0x3d62bcf1,
0x3d353d35,0xbd62bcf1,0x3d7b3c48,0xbd7f3bc9,0x3d6dbcc4,0xbd463d22,0x3d0ebd55,0xbc953d75,0xbd800000,0x3d75bc95,0xbd553d0e,0x3d22bd46,0xbcc43d6d,0x3bc9bd7f,0x3c483d7b,0xbcf1bd62,
0x3d6d3cc4,0xbd75bc95,0x3d7b3c48,0xbd7fbbc9,0x3d353d35,0xbd46bd22,0x3d553d0e,0xbd62bcf1,0x3cc43d6d,0xbcf1bd62,0x3d0e3d55,0xbd22bd46,0x80003d80,0xbbc9bd7f,0x3c483d7b,0xbc95bd75,
0xbcc43d6d,0x3c95bd75,0xbc483d7b,0x3bc9bd7f,0xbd353d35,0x3d22bd46,0xbd0e3d55,0x3cf1bd62,0xbd6d3cc4,0x3d62bcf1,0xbd553d0e,0x3d46bd22,0xbd800000,0x3d7fbbc9,0xbd7b3c48,0x3d75bc95,
0x3d80,0x3bc9bd7f,0xbc483d7b,0x3c95bd75,0xbcc43d6d,0x3cf1bd62,0xbd0e3d55,0x3d22bd46,0xbd353d35,0x3d46bd22,0xbd553d0e,0x3d62bcf1,0xbd6d3cc4,0x3d75bc95,0xbd7b3c48,0x3d7fbbc9,
0xbd800000,0x3d7f3bc9,0xbd7bbc48,0x3d753c95,0xbd6dbcc4,0x3d623cf1,0xbd55bd0e,0x3d463d22,0xbd35bd35,0x3d223d46,0xbd0ebd55,0x3cf13d62,0xbcc4bd6d,0x3c953d75,0xbc48bd7b,0x3bc93d7f,
0xbd6d3cc4,0x3d7fbbc9,0xbd7bbc48,0x3d623cf1,0x3d80,0x3c95bd75,0xbd0e3d55,0x3d46bd22,0x3cc4bd6d,0xbd223d46,0x3d55bd0e,0xbd753c95,0xbd35bd35,0x3cf13d62,0xbc48bd7b,0xbbc93d7f,
0x3cc43d6d,0xbbc9bd7f,0xbc483d7b,0x3cf1bd62,0x3d800000,0xbd75bc95,0x3d553d0e,0xbd22bd46,0xbd6dbcc4,0x3d463d22,0xbd0ebd55,0x3c953d75,0xbd353d35,0x3d62bcf1,0xbd7b3c48,0x3d7f3bc9,
0x3d35bd35,0xbd753c95,0x3d7b3c48,0xbd46bd22,0x3cc43d6d,0x3bc9bd7f,0xbd0e3d55,0x3d62bcf1,0x3d80,0x3cf1bd62,0xbd553d0e,0x3d7fbbc9,0xbd6dbcc4,0x3d223d46,0xbc48bd7b,0xbc953d75,
0x3d353d35,0xbc95bd75,0xbc483d7b,0x3d22bd46,0xbd6d3cc4,0x3d7f3bc9,0xbd55bd0e,0x3cf13d62,0xbd800000,0x3d623cf1,0xbd0ebd55,0x3bc93d7f,0x3cc4bd6d,0xbd463d22,0x3d7bbc48,0xbd75bc95,
0xbd6dbcc4,0x3cf13d62,0x3c48bd7b,0xbd463d22,0x3d353d35,0xbbc9bd7f,0xbd0e3d55,0x3d75bc95,0xbcc4bd6d,0xbc953d75,0x3d55bd0e,0xbd7fbbc9,0x3d80,0x3d22bd46,0xbd7b3c48,0x3d623cf1,
0xbcc43d6d,0x3d62bcf1,0xbd7bbc48,0x3d223d46,0x3d35bd35,0xbd7f3bc9,0x3d553d0e,0xbc95bd75,0xbd6d3cc4,0x3d753c95,0xbd0ebd55,0xbbc93d7f,0x3d800000,0xbd46bd22,0x3c483d7b,0x3cf1bd62,
0xbd800000,0x3d223d46,0x3c48bd7b,0xbd623cf1,0x3d6d3cc4,0xbc95bd75,0xbd0e3d55,0x3d7fbbc9,0xbd35bd35,0xbbc93d7f,0x3d55bd0e,0xbd75bc95,0x3cc43d6d,0x3cf1bd62,0xbd7b3c48,0x3d463d22,
0x3d80,0x3d46bd22,0xbd7bbc48,0x3cf13d62,0x3cc4bd6d,0xbd753c95,0x3d553d0e,0xbbc9bd7f,0xbd353d35,0x3d7f3bc9,0xbd0ebd55,0xbc953d75,0x3d6dbcc4,0xbd62bcf1,0x3c483d7b,0x3d22bd46,
0xbcc4bd6d,0xbd223d46,0x3d7b3c48,0xbc95bd75,0x3d800000,0xbcf1bd62,0xbd0e3d55,0x3d7f3bc9,0x3d6d3cc4,0xbbc9bd7f,0xbd553d0e,0x3d623cf1,0xbd353d35,0x3d753c95,0xbc48bd7b,0xbd463d22,
0x3d6dbcc4,0xbd46bd22,0xbc483d7b,0x3d75bc95,0x3d80,0x3d62bcf1,0xbd55bd0e,0xbbc93d7f,0xbcc43d6d,0x3d7fbbc9,0xbd0ebd55,0xbcf13d62,0xbd35bd35,0xbc953d75,0x3d7bbc48,0xbd22bd46,
0x3d353d35,0x3cf1bd62,0xbd7bbc48,0x3bc93d7f,0x3d6dbcc4,0xbd22bd46,0xbd0e3d55,0x3d753c95,0xbd800000,0x3c953d75,0x3d55bd0e,0xbd46bd22,0xbcc43d6d,0x3d7f3bc9,0xbc48bd7b,0xbd623cf1,
0x3d35bd35,0xbd62bcf1,0xbc483d7b,0x3d7fbbc9,0xbcc4bd6d,0xbd463d22,0x3d553d0e,0x3c95bd75,0x3d80,0x3d75bc95,0xbd0ebd55,0xbd223d46,0x3d6d3cc4,0x3bc9bd7f,0xbd7b3c48,0x3cf13d62,
0x3cc4bd6d,0xbd75bc95,0xbc483d7b,0x3d7f3bc9,0x3d35bd35,0xbd46bd22,0xbd0e3d55,0x3d623cf1,0x3d6dbcc4,0xbcf1bd62,0xbd553d0e,0x3d223d46,0x3d800000,0xbbc9bd7f,0xbd7b3c48,0x3c953d75,
0x3d6d3cc4,0x3c95bd75,0xbd7bbc48,0xbbc93d7f,0x3d353d35,0x3d22bd46,0xbd55bd0e,0xbcf13d62,0x3cc43d6d,0x3d62bcf1,0xbd0ebd55,0xbd463d22,0x3d80,0x3d7fbbc9,0xbc48bd7b,0xbd753c95,
0xbd800000,0x3d7f3bc9,0xbd7bbc48,0x3d753c95,0xbd6dbcc4,0x3d623cf1,0xbd55bd0e,0x3d463d22,0xbd35bd35,0x3d223d46,0xbd0ebd55,0x3cf13d62,0xbcc4bd6d,0x3c953d75,0xbc48bd7b,0x3bc93d7f,
0x8000bd80,0xbbc93d7f,0x3c48bd7b,0xbc953d75,0x3cc4bd6d,0xbcf13d62,0x3d0ebd55,0xbd223d46,0x3d35bd35,0xbd463d22,0x3d55bd0e,0xbd623cf1,0x3d6dbcc4,0xbd753c95,0x3d7bbc48,0xbd7f3bc9,
0xbcc4bd6d,0x3bc93d7f,0x3c48bd7b,0xbcf13d62,0xbd800000,0x3d753c95,0xbd55bd0e,0x3d223d46,0x3d6d3cc4,0xbd46bd22,0x3d0e3d55,0xbc95bd75,0x3d35bd35,0xbd623cf1,0x3d7bbc48,0xbd7fbbc9,
0xbd6d3cc4,0x3d7fbbc9,0xbd7bbc48,0x3d623cf1,0x80003d80,0x3c95bd75,0xbd0e3d55,0x3d46bd22,0x3cc4bd6d,0xbd223d46,0x3d55bd0e,0xbd753c95,0xbd35bd35,0x3cf13d62,0xbc48bd7b,0xbbc93d7f,
0x3d353d35,0xbc95bd75,0xbc483d7b,0x3d22bd46,0xbd6d3cc4,0x3d7f3bc9,0xbd55bd0e,0x3cf13d62,0xbd800000,0x3d623cf1,0xbd0ebd55,0x3bc93d7f,0x3cc4bd6d,0xbd463d22,0x3d7bbc48,0xbd75bc95,
0xbd353d35,0x3d75bc95,0xbd7bbc48,0x3d463d22,0xbcc4bd6d,0xbbc93d7f,0x3d0ebd55,0xbd623cf1,0x8000bd80,0xbcf13d62,0x3d55bd0e,0xbd7f3bc9,0x3d6d3cc4,0xbd22bd46,0x3c483d7b,0x3c95bd75,
0x3cc4bd6d,0xbd623cf1,0x3d7b3c48,0xbd22bd46,0xbd353d35,0x3d7fbbc9,0xbd55bd0e,0x3c953d75,0x3d6dbcc4,0xbd75bc95,0x3d0e3d55,0x3bc9bd7f,0xbd800000,0x3d463d22,0xbc48bd7b,0xbcf13d62,
0xbd6dbcc4,0x3cf13d62,0x3c48bd7b,0xbd463d22,0x3d353d35,0xbbc9bd7f,0xbd0e3d55,0x3d75bc95,0xbcc4bd6d,0xbc953d75,0x3d55bd0e,0xbd7fbbc9,0x80003d80,0x3d22bd46,0xbd7b3c48,0x3d623cf1,
0x8000bd80,0xbd463d22,0x3d7b3c48,0xbcf1bd62,0xbcc43d6d,0x3d75bc95,0xbd55bd0e,0x3bc93d7f,0x3d35bd35,0xbd7fbbc9,0x3d0e3d55,0x3c95bd75,0xbd6d3cc4,0x3d623cf1,0xbc48bd7b,0xbd223d46,
0xbd800000,0x3d223d46,0x3c48bd7b,0xbd623cf1,0x3d6d3cc4,0xbc95bd75,0xbd0e3d55,0x3d7fbbc9,0xbd35bd35,0xbbc93d7f,0x3d55bd0e,0xbd75bc95,0x3cc43d6d,0x3cf1bd62,0xbd7b3c48,0x3d463d22,
0x3d6dbcc4,0xbd46bd22,0xbc483d7b,0x3d75bc95,0x80003d80,0x3d62bcf1,0xbd55bd0e,0xbbc93d7f,0xbcc43d6d,0x3d7fbbc9,0xbd0ebd55,0xbcf13d62,0xbd35bd35,0xbc953d75,0x3d7bbc48,0xbd22bd46,
0x3cc43d6d,0x3d22bd46,0xbd7bbc48,0x3c953d75,0xbd800000,0x3cf13d62,0x3d0ebd55,0xbd7fbbc9,0xbd6dbcc4,0x3bc93d7f,0x3d55bd0e,0xbd62bcf1,0x3d35bd35,0xbd75bc95,0x3c483d7b,0x3d46bd22,
0xbd353d35,0x3d623cf1,0x3c48bd7b,0xbd7f3bc9,0x3cc43d6d,0x3d46bd22,0xbd55bd0e,0xbc953d75,0x8000bd80,0xbd753c95,0x3d0e3d55,0x3d22bd46,0xbd6dbcc4,0xbbc93d7f,0x3d7bbc48,0xbcf1bd62,
0x3d353d35,0x3cf1bd62,0xbd7bbc48,0x3bc93d7f,0x3d6dbcc4,0xbd22bd46,0xbd0e3d55,0x3d753c95,0xbd800000,0x3c953d75,0x3d55bd0e,0xbd46bd22,0xbcc43d6d,0x3d7f3bc9,0xbc48bd7b,0xbd623cf1,
0x3d6d3cc4,0x3c95bd75,0xbd7bbc48,0xbbc93d7f,0x3d353d35,0x3d22bd46,0xbd55bd0e,0xbcf13d62,0x3cc43d6d,0x3d62bcf1,0xbd0ebd55,0xbd463d22,0x80003d80,0x3d7fbbc9,0xbc48bd7b,0xbd753c95,
0xbcc43d6d,0x3d753c95,0x3c48bd7b,0xbd7fbbc9,0xbd353d35,0x3d463d22,0x3d0ebd55,0xbd62bcf1,0xbd6d3cc4,0x3cf13d62,0x3d55bd0e,0xbd22bd46,0xbd800000,0x3bc93d7f,0x3d7bbc48,0xbc95bd75,
0x3d80,0x3d7f3bc9,0x3c48bd7b,0xbd75bc95,0xbcc43d6d,0x3d623cf1,0x3d0ebd55,0xbd46bd22,0xbd353d35,0x3d223d46,0x3d55bd0e,0xbcf1bd62,0xbd6d3cc4,0x3c953d75,0x3d7bbc48,0xbbc9bd7f,
0xbd800000,0xbbc93d7f,0x3d7b3c48,0x3c95bd75,0xbd6dbcc4,0xbcf13d62,0x3d553d0e,0x3d22bd46,0xbd35bd35,0xbd463d22,0x3d0e3d55,0x3d62bcf1,0xbcc4bd6d,0xbd753c95,0x3c483d7b,0x3d7fbbc9,
0xbd6d3cc4,0x3bc93d7f,0x3d7b3c48,0x3cf1bd62,0x3d80,0x3d753c95,0x3d0ebd55,0xbd22bd46,0x3cc4bd6d,0xbd46bd22,0xbd553d0e,0x3c953d75,0xbd35bd35,0xbd623cf1,0x3c483d7b,0x3d7f3bc9,
0x3cc43d6d,0x3d7fbbc9,0x3c48bd7b,0xbd62bcf1,0x3d800000,0x3c95bd75,0xbd55bd0e,0xbd463d22,0xbd6dbcc4,0xbd223d46,0x3d0e3d55,0x3d75bc95,0xbd353d35,0x3cf13d62,0x3d7bbc48,0x3bc9bd7f,
0x3d35bd35,0xbc95bd75,0xbd7bbc48,0xbd223d46,0x3cc43d6d,0x3d7f3bc9,0x3d0ebd55,0xbcf1bd62,0x3d80,0x3d623cf1,0x3d55bd0e,0xbbc9bd7f,0xbd6dbcc4,0xbd463d22,0x3c483d7b,0x3d753c95,
0x3d353d35,0x3d75bc95,0x3c48bd7b,0xbd46bd22,0xbd6d3cc4,0xbbc93d7f,0x3d553d0e,0x3d62bcf1,0xbd800000,0xbcf13d62,0x3d0e3d55,0x3d7fbbc9,0x3cc4bd6d,0xbd22bd46,0xbd7b3c48,0xbc953d75,
0xbd6dbcc4,0xbd623cf1,0xbc483d7b,0x3d223d46,0x3d353d35,0x3d7fbbc9,0x3d0ebd55,0xbc95bd75,0xbcc4bd6d,0xbd75bc95,0xbd553d0e,0xbbc93d7f,0x3d80,0x3d463d22,0x3d7bbc48,0x3cf1bd62,
0xbcc43d6d,0x3cf13d62,0x3d7b3c48,0x3d46bd22,0x3d35bd35,0xbbc9bd7f,0xbd55bd0e,0xbd753c95,0xbd6d3cc4,0xbc953d75,0x3d0e3d55,0x3d7f3bc9,0x3d800000,0x3d22bd46,0xbc48bd7b,0xbd62bcf1,
0xbd800000,0xbd463d22,0xbc483d7b,0x3cf13d62,0x3d6d3cc4,0x3d75bc95,0x3d0ebd55,0xbbc9bd7f,0xbd35bd35,0xbd7fbbc9,0xbd553d0e,0xbc953d75,0x3cc43d6d,0x3d623cf1,0x3d7bbc48,0x3d22bd46,
0x3d80,0x3d223d46,0x3d7b3c48,0x3d62bcf1,0x3cc4bd6d,0xbc95bd75,0xbd55bd0e,0xbd7f3bc9,0xbd353d35,0xbbc93d7f,0x3d0e3d55,0x3d753c95,0x3d6dbcc4,0x3cf1bd62,0xbc48bd7b,0xbd46bd22,
0xbcc4bd6d,0xbd46bd22,0xbd7bbc48,0xbd753c95,0x3d800000,0x3d62bcf1,0x3d0ebd55,0x3bc9bd7f,0x3d6d3cc4,0x3d7fbbc9,0x3d55bd0e,0x3cf1bd62,0xbd353d35,0xbc953d75,0x3c483d7b,0x3d223d46,
0x3d6dbcc4,0x3d22bd46,0x3c48bd7b,0xbc95bd75,0x3d80,0x3cf13d62,0x3d553d0e,0x3d7f3bc9,0xbcc43d6d,0x3bc93d7f,0x3d0e3d55,0x3d623cf1,0xbd35bd35,0xbd75bc95,0xbd7b3c48,0xbd463d22,
0x3d353d35,0x3d623cf1,0x3d7b3c48,0x3d7fbbc9,0x3d6dbcc4,0x3d46bd22,0x3d0ebd55,0x3c95bd75,0xbd800000,0xbd753c95,0xbd553d0e,0xbd223d46,0xbcc43d6d,0xbbc93d7f,0x3c483d7b,0x3cf13d62,
0x3d35bd35,0x3cf1bd62,0x3c48bd7b,0xbbc9bd7f,0xbcc4bd6d,0xbd22bd46,0xbd55bd0e,0xbd75bc95,0x3d80,0x3c953d75,0x3d0e3d55,0x3d463d22,0x3d6d3cc4,0x3d7f3bc9,0x3d7bbc48,0x3d62bcf1,
0x3cc4bd6d,0x3c95bd75,0x3c48bd7b,0x3bc9bd7f,0x3d35bd35,0x3d22bd46,0x3d0ebd55,0x3cf1bd62,0x3d6dbcc4,0x3d62bcf1,0x3d55bd0e,0x3d46bd22,0x3d800000,0x3d7fbbc9,0x3d7bbc48,0x3d75bc95,
0x3d6d3cc4,0x3d753c95,0x3d7b3c48,0x3d7f3bc9,0x3d353d35,0x3d463d22,0x3d553d0e,0x3d623cf1,0x3cc43d6d,0x3cf13d62,0x3d0e3d55,0x3d223d46,0x3d80,0x3bc93d7f,0x3c483d7b,0x3c953d75,
0xbd800000,0xbbc93d7f,0x3d7b3c48,0x3c95bd75,0xbd6dbcc4,0xbcf13d62,0x3d553d0e,0x3d22bd46,0xbd35bd35,0xbd463d22,0x3d0e3d55,0x3d62bcf1,0xbcc4bd6d,0xbd753c95,0x3c483d7b,0x3d7fbbc9,
0x8000bd80,0xbd7fbbc9,0xbc483d7b,0x3d753c95,0x3cc4bd6d,0xbd62bcf1,0xbd0e3d55,0x3d463d22,0x3d35bd35,0xbd22bd46,0xbd553d0e,0x3cf13d62,0x3d6dbcc4,0xbc95bd75,0xbd7b3c48,0x3bc93d7f,
0xbcc4bd6d,0xbd7f3bc9,0xbc483d7b,0x3d623cf1,0xbd800000,0xbc953d75,0x3d553d0e,0x3d46bd22,0x3d6d3cc4,0x3d22bd46,0xbd0ebd55,0xbd753c95,0x3d35bd35,0xbcf1bd62,0xbd7b3c48,0xbbc93d7f,
0xbd6d3cc4,0x3bc93d7f,0x3d7b3c48,0x3cf1bd62,0x80003d80,0x3d753c95,0x3d0ebd55,0xbd22bd46,0x3cc4bd6d,0xbd46bd22,0xbd553d0e,0x3c953d75,0xbd35bd35,0xbd623cf1,0x3c483d7b,0x3d7f3bc9,
0x3d353d35,0x3d75bc95,0x3c48bd7b,0xbd46bd22,0xbd6d3cc4,0xbbc93d7f,0x3d553d0e,0x3d62bcf1,0xbd800000,0xbcf13d62,0x3d0e3d55,0x3d7fbbc9,0x3cc4bd6d,0xbd22bd46,0xbd7b3c48,0xbc953d75,
0xbd353d35,0x3c953d75,0x3d7b3c48,0x3d22bd46,0xbcc4bd6d,0xbd7fbbc9,0xbd0e3d55,0x3cf13d62,0x8000bd80,0xbd62bcf1,0xbd553d0e,0x3bc93d7f,0x3d6d3cc4,0x3d46bd22,0xbc48bd7b,0xbd75bc95,
0x3cc4bd6d,0xbcf1bd62,0xbd7bbc48,0xbd463d22,0xbd353d35,0x3bc93d7f,0x3d553d0e,0x3d75bc95,0x3d6dbcc4,0x3c95bd75,0xbd0ebd55,0xbd7fbbc9,0xbd800000,0xbd223d46,0x3c483d7b,0x3d623cf1,
0xbd6dbcc4,0xbd623cf1,0xbc483d7b,0x3d223d46,0x3d353d35,0x3d7fbbc9,0x3d0ebd55,0xbc95bd75,0xbcc4bd6d,0xbd75bc95,0xbd553d0e,0xbbc93d7f,0x80003d80,0x3d463d22,0x3d7bbc48,0x3cf1bd62,
0x8000bd80,0xbd22bd46,0xbd7bbc48,0xbd623cf1,0xbcc43d6d,0x3c953d75,0x3d553d0e,0x3d7fbbc9,0x3d35bd35,0x3bc9bd7f,0xbd0ebd55,0xbd75bc95,0xbd6d3cc4,0xbcf13d62,0x3c483d7b,0x3d463d22,
0xbd800000,0xbd463d22,0xbc483d7b,0x3cf13d62,0x3d6d3cc4,0x3d75bc95,0x3d0ebd55,0xbbc9bd7f,0xbd35bd35,0xbd7fbbc9,0xbd553d0e,0xbc953d75,0x3cc43d6d,0x3d623cf1,0x3d7bbc48,0x3d22bd46,
0x3d6dbcc4,0x3d22bd46,0x3c48bd7b,0xbc95bd75,0x80003d80,0x3cf13d62,0x3d553d0e,0x3d7f3bc9,0xbcc43d6d,0x3bc93d7f,0x3d0e3d55,0x3d623cf1,0xbd35bd35,0xbd75bc95,0xbd7b3c48,0xbd463d22,
0x3cc43d6d,0x3d463d22,0x3d7b3c48,0x3d75bc95,0xbd800000,0xbd623cf1,0xbd0e3d55,0xbbc93d7f,0xbd6dbcc4,0xbd7f3bc9,0xbd553d0e,0xbcf13d62,0x3d35bd35,0x3c95bd75,0xbc48bd7b,0xbd22bd46,
0xbd353d35,0xbcf13d62,0xbc483d7b,0x3bc93d7f,0x3cc43d6d,0x3d223d46,0x3d553d0e,0x3d753c95,0x8000bd80,0xbc95bd75,0xbd0ebd55,0xbd46bd22,0xbd6dbcc4,0xbd7fbbc9,0xbd7b3c48,0xbd623cf1,
0x3d353d35,0x3d623cf1,0x3d7b3c48,0x3d7fbbc9,0x3d6dbcc4,0x3d46bd22,0x3d0ebd55,0x3c95bd75,0xbd800000,0xbd753c95,0xbd553d0e,0xbd223d46,0xbcc43d6d,0xbbc93d7f,0x3c483d7b,0x3cf13d62,
0x3d6d3cc4,0x3d753c95,0x3d7b3c48,0x3d7f3bc9,0x3d353d35,0x3d463d22,0x3d553d0e,0x3d623cf1,0x3cc43d6d,0x3cf13d62,0x3d0e3d55,0x3d223d46,0x80003d80,0x3bc93d7f,0x3c483d7b,0x3c953d75,
0xbcc43d6d,0xbc953d75,0xbc483d7b,0xbbc93d7f,0xbd353d35,0xbd223d46,0xbd0e3d55,0xbcf13d62,0xbd6d3cc4,0xbd623cf1,0xbd553d0e,0xbd463d22,0xbd800000,0xbd7f3bc9,0xbd7b3c48,0xbd753c95,
0x3d80,0xbc163d7d,0xbc953d75,0xbcdb3d67,0xbd0e3d55,0xbd2c3d3e,0xbd463d22,0xbd5c3d04,0xbd6d3cc4,0xbd783c79,0xbd7f3bc9,0xbd80bb49,0xbd7bbc48,0xbd71bcac,0xbd62bcf1,0xbd4ebd18,
0xbd35bd35,0xbd18bd4e,0xbcf1bd62,0xbcacbd71,0xbc48bd7b,0xbb49bd80,0x3bc9bd7f,0x3c79bd78,0x3cc4bd6d,0x3d04bd5c,0x3d22bd46,0x3d3ebd2c,0x3d55bd0e,0x3d67bcdb,0x3d75bc95,0x3d7dbc16,
0xbd7b3c48,0xbd7dbc16,0xbd62bcf1,0xbd2cbd3e,0x3d80,0xbcac3d71,0xbd223d46,0xbd5c3d04,0x3d55bd0e,0x3d78bc79,0x3d7f3bc9,0x3d673cdb,0xbcc4bd6d,0xbb49bd80,0x3c95bd75,0x3d18bd4e,
0xbd0e3d55,0xbd4e3d18,0xbd753c95,0xbd80bb49,0x3d353d35,0x3cdb3d67,0x3bc93d7f,0xbc793d78,0x3c48bd7b,0x3d04bd5c,0x3d46bd22,0x3d71bcac,0xbd6dbcc4,0xbd3ebd2c,0xbcf1bd62,0xbc16bd7d,
0x3d6dbcc4,0x3d7d3c16,0x3d463d22,0x3cac3d71,0xbc483d7b,0xbd2c3d3e,0xbd753c95,0xbd78bc79,0x3d80,0xbd043d5c,0xbd623cf1,0xbd80bb49,0xbd55bd0e,0xbcdbbd67,0x3bc9bd7f,0x3d18bd4e,
0xbcc43d6d,0xbd4e3d18,0xbd7f3bc9,0xbd67bcdb,0xbd0ebd55,0xbb49bd80,0x3cf1bd62,0x3d5cbd04,0xbd35bd35,0xbc79bd78,0x3c95bd75,0x3d3ebd2c,0x3d7bbc48,0x3d713cac,0x3d223d46,0x3c163d7d,
0xbd0ebd55,0x3c16bd7d,0x3d46bd22,0x3d803b49,0x3cc43d6d,0xbcac3d71,0xbd623cf1,0xbd78bc79,0xbc48bd7b,0x3d04bd5c,0x3d75bc95,0x3d673cdb,0x3d80,0xbd2c3d3e,0xbd7f3bc9,0xbd4ebd18,
0xbd7bbc48,0xbd18bd4e,0x3bc9bd7f,0x3d3ebd2c,0x3d6d3cc4,0x3cdb3d67,0xbc953d75,0xbd5c3d04,0xbd55bd0e,0xbc79bd78,0x3cf1bd62,0x3d71bcac,0x3d353d35,0x3b493d80,0xbd223d46,0xbd7d3c16,
0xbd35bd35,0x3c16bd7d,0x3d62bcf1,0x3d673cdb,0x3c483d7b,0xbd2c3d3e,0xbd7fbbc9,0xbd04bd5c,0x3cc4bd6d,0x3d78bc79,0x3d463d22,0xbb493d80,0xbd553d0e,0xbd71bcac,0xbc95bd75,0x3d18bd4e,
0x3d80,0xbd4e3d18,0xbd75bc95,0xbcacbd71,0x3d0ebd55,0x3d80bb49,0x3d223d46,0xbc793d78,0xbd6d3cc4,0xbd5cbd04,0xbbc9bd7f,0x3d3ebd2c,0x3d7b3c48,0x3cdb3d67,0xbcf13d62,0xbd7d3c16,
0x3d0ebd55,0x3d7d3c16,0x3c953d75,0xbd3e3d2c,0x3d353d35,0xbcac3d71,0xbd7f3bc9,0xbd04bd5c,0xbc483d7b,0xbd783c79,0xbd22bd46,0x3cdbbd67,0xbd6dbcc4,0xbb49bd80,0x3d62bcf1,0x3d4e3d18,
0x3d7bbc48,0x3d183d4e,0xbcf13d62,0xbd80bb49,0x3d80,0xbd673cdb,0xbd46bd22,0x3c79bd78,0xbd553d0e,0xbd5cbd04,0x3bc9bd7f,0x3d71bcac,0xbcc4bd6d,0x3d2cbd3e,0x3d753c95,0x3c163d7d,
0xbcc43d6d,0xbd7dbc16,0xbbc9bd7f,0x3d71bcac,0x3d0e3d55,0xbd2c3d3e,0xbd62bcf1,0x3c79bd78,0xbd35bd35,0x3d04bd5c,0x3d753c95,0xbb493d80,0xbd7b3c48,0xbcdbbd67,0x3d46bd22,0x3d4e3d18,
0x3d6dbcc4,0x3d183d4e,0xbd223d46,0xbd67bcdb,0x3c48bd7b,0x3d80bb49,0x3c953d75,0xbd5c3d04,0x3d80,0xbd783c79,0xbcf1bd62,0x3d3ebd2c,0x3d553d0e,0xbcac3d71,0xbd7fbbc9,0xbc16bd7d,
0x3d7b3c48,0xbc163d7d,0xbd7fbbc9,0x3b49bd80,0x3d6d3cc4,0xbcac3d71,0xbd75bc95,0x3c79bd78,0x3d553d0e,0xbd043d5c,0xbd62bcf1,0x3cdbbd67,0x3d353d35,0xbd2c3d3e,0xbd46bd22,0x3d18bd4e,
0x3d0e3d55,0xbd4e3d18,0xbd22bd46,0x3d3ebd2c,0x3cc43d6d,0xbd673cdb,0xbcf1bd62,0x3d5cbd04,0x3c483d7b,0xbd783c79,0xbc95bd75,0x3d71bcac,0x3d80,0xbd803b49,0xbbc9bd7f,0x3d7dbc16,
0xbd800000,0xbd7dbc16,0xbd75bc95,0xbd67bcdb,0xbd55bd0e,0xbd3ebd2c,0xbd22bd46,0xbd04bd5c,0xbcc4bd6d,0xbc79bd78,0xbbc9bd7f,0x3b49bd80,0x3c48bd7b,0x3cacbd71,0x3cf1bd62,0x3d18bd4e,
0x3d35bd35,0x3d4ebd18,0x3d62bcf1,0x3d71bcac,0x3d7bbc48,0x3d80bb49,0x3d7f3bc9,0x3d783c79,0x3d6d3cc4,0x3d5c3d04,0x3d463d22,0x3d2c3d3e,0x3d0e3d55,0x3cdb3d67,0x3c953d75,0x3c163d7d,
0xbc48bd7b,0x3c16bd7d,0x3cf1bd62,0x3d3ebd2c,0xbd800000,0xbd71bcac,0xbd46bd22,0xbd04bd5c,0x3d0e3d55,0x3c793d78,0xbbc93d7f,0xbcdb3d67,0x3d6dbcc4,0x3d80bb49,0x3d753c95,0x3d4e3d18,
0xbd55bd0e,0xbd18bd4e,0xbc95bd75,0x3b49bd80,0xbd353d35,0xbd673cdb,0xbd7f3bc9,0xbd78bc79,0x3d7b3c48,0x3d5c3d04,0x3d223d46,0x3cac3d71,0x3cc4bd6d,0x3d2cbd3e,0x3d62bcf1,0x3d7dbc16,
0x3cc43d6d,0xbc163d7d,0xbd223d46,0xbd713cac,0xbd7bbc48,0xbd3ebd2c,0xbc95bd75,0x3c79bd78,0xbd800000,0xbd5cbd04,0xbcf1bd62,0x3b49bd80,0x3d0ebd55,0x3d67bcdb,0x3d7f3bc9,0x3d4e3d18,
0xbd6dbcc4,0xbd18bd4e,0xbbc9bd7f,0x3cdbbd67,0x3d55bd0e,0x3d80bb49,0x3d623cf1,0x3d043d5c,0x3d35bd35,0x3d78bc79,0x3d753c95,0x3d2c3d3e,0x3c483d7b,0xbcac3d71,0xbd463d22,0xbd7d3c16,
0x3d55bd0e,0x3d7d3c16,0x3d223d46,0xbb493d80,0xbd6d3cc4,0xbd71bcac,0xbcf1bd62,0x3c79bd78,0x3d7bbc48,0x3d5c3d04,0x3c953d75,0xbcdb3d67,0xbd800000,0xbd3ebd2c,0xbbc9bd7f,0x3d18bd4e,
0x3c48bd7b,0x3d4ebd18,0x3d7f3bc9,0x3d2c3d3e,0xbcc43d6d,0xbd673cdb,0xbd75bc95,0xbd04bd5c,0x3d0ebd55,0x3d78bc79,0x3d623cf1,0x3cac3d71,0xbd353d35,0xbd803b49,0xbd46bd22,0xbc16bd7d,
0x3d35bd35,0x3d7d3c16,0x3cf13d62,0xbcdb3d67,0xbd7b3c48,0xbd3ebd2c,0x3bc9bd7f,0x3d5cbd04,0x3d6d3cc4,0x3c793d78,0xbd223d46,0xbd80bb49,0xbd0ebd55,0x3cacbd71,0x3d75bc95,0x3d4e3d18,
0xbd800000,0xbd18bd4e,0x3c95bd75,0x3d71bcac,0x3d553d0e,0x3b493d80,0xbd463d22,0xbd78bc79,0xbcc4bd6d,0x3d04bd5c,0x3d7fbbc9,0x3d2c3d3e,0xbc483d7b,0xbd673cdb,0xbd62bcf1,0xbc16bd7d,
0x3d553d0e,0xbc163d7d,0xbd753c95,0xbd2cbd3e,0xbd353d35,0xbd71bcac,0xbbc9bd7f,0x3d5cbd04,0xbd7bbc48,0xbc79bd78,0x3d46bd22,0x3d673cdb,0x3cc4bd6d,0x3d80bb49,0x3cf13d62,0xbd183d4e,
0x3c483d7b,0xbd4e3d18,0xbd62bcf1,0x3b49bd80,0xbd800000,0xbcdbbd67,0x3d22bd46,0x3d783c79,0xbd0ebd55,0x3d04bd5c,0x3d7f3bc9,0x3cac3d71,0x3d6dbcc4,0x3d3e3d2c,0xbc953d75,0xbd7d3c16,
0xbd6dbcc4,0x3c16bd7d,0x3d7fbbc9,0x3cac3d71,0xbd553d0e,0xbd3ebd2c,0x3cf1bd62,0x3d783c79,0x3d35bd35,0x3d5c3d04,0xbc953d75,0xbd80bb49,0xbc48bd7b,0x3d67bcdb,0x3d223d46,0xbd183d4e,
0x3cc43d6d,0xbd4e3d18,0xbd46bd22,0x3cdbbd67,0x3d7b3c48,0x3b493d80,0xbd753c95,0xbd04bd5c,0xbd800000,0xbc79bd78,0x3d62bcf1,0x3d2c3d3e,0xbd0e3d55,0xbd71bcac,0x3bc9bd7f,0x3d7dbc16,
0xbc483d7b,0xbd7dbc16,0x3bc9bd7f,0x3d803b49,0xbcc43d6d,0xbd71bcac,0x3c95bd75,0x3d783c79,0xbd0e3d55,0xbd5cbd04,0x3cf1bd62,0x3d673cdb,0xbd353d35,0xbd3ebd2c,0x3d22bd46,0x3d4e3d18,
0xbd553d0e,0xbd18bd4e,0x3d46bd22,0x3d2c3d3e,0xbd6d3cc4,0xbcdbbd67,0x3d62bcf1,0x3d043d5c,0xbd7b3c48,0xbc79bd78,0x3d75bc95,0x3cac3d71,0xbd800000,0xbb49bd80,0x3d7fbbc9,0x3c163d7d,
0x3d80,0xbd7dbc16,0x3c95bd75,0x3d673cdb,0xbd0e3d55,0xbd3ebd2c,0x3d46bd22,0x3d043d5c,0xbd6d3cc4,0xbc79bd78,0x3d7fbbc9,0xbb493d80,0xbd7bbc48,0x3cacbd71,0x3d623cf1,0xbd183d4e,
0xbd35bd35,0x3d4ebd18,0x3cf13d62,0xbd713cac,0xbc48bd7b,0x3d80bb49,0xbbc93d7f,0xbd78bc79,0x3cc4bd6d,0x3d5c3d04,0xbd223d46,0xbd2cbd3e,0x3d55bd0e,0x3cdb3d67,0xbd753c95,0xbc16bd7d,
0xbd7b3c48,0x3c16bd7d,0x3d623cf1,0xbd3e3d2c,0x3d80,0xbd71bcac,0x3d22bd46,0x3d043d5c,0x3d55bd0e,0x3c793d78,0xbd7fbbc9,0x3cdbbd67,0xbcc4bd6d,0x3d80bb49,0xbc953d75,0xbd4ebd18,
0xbd0e3d55,0xbd18bd4e,0x3d75bc95,0xbb493d80,0x3d353d35,0xbd673cdb,0xbbc9bd7f,0x3d783c79,0x3c48bd7b,0x3d5c3d04,0xbd463d22,0xbcacbd71,0xbd6dbcc4,0x3d2cbd3e,0x3cf13d62,0xbd7d3c16,
0x3d6dbcc4,0xbc163d7d,0xbd46bd22,0x3d71bcac,0xbc483d7b,0xbd3ebd2c,0x3d75bc95,0xbc793d78,0x3d80,0xbd5cbd04,0x3d62bcf1,0xbb493d80,0xbd55bd0e,0x3d67bcdb,0xbbc93d7f,0xbd4ebd18,
0xbcc43d6d,0xbd18bd4e,0x3d7fbbc9,0xbcdb3d67,0xbd0ebd55,0x3d80bb49,0xbcf13d62,0xbd04bd5c,0xbd35bd35,0x3d78bc79,0xbc953d75,0xbd2cbd3e,0x3d7bbc48,0xbcac3d71,0xbd22bd46,0x3d7dbc16,
0xbd0ebd55,0x3d7d3c16,0xbd463d22,0x3b49bd80,0x3cc43d6d,0xbd71bcac,0x3d62bcf1,0xbc793d78,0xbc48bd7b,0x3d5c3d04,0xbd753c95,0x3cdbbd67,0x3d80,0xbd3ebd2c,0x3d7fbbc9,0xbd183d4e,
0xbd7bbc48,0x3d4ebd18,0xbbc93d7f,0xbd2cbd3e,0x3d6d3cc4,0xbd673cdb,0x3c95bd75,0x3d043d5c,0xbd55bd0e,0x3d78bc79,0xbcf13d62,0xbcacbd71,0x3d353d35,0xbd803b49,0x3d22bd46,0x3c163d7d,
0xbd35bd35,0x3d7d3c16,0xbd623cf1,0x3cdbbd67,0x3c483d7b,0xbd3ebd2c,0x3d7f3bc9,0xbd5c3d04,0x3cc4bd6d,0x3c793d78,0xbd46bd22,0x3d803b49,0xbd553d0e,0x3cacbd71,0x3c953d75,0xbd4ebd18,
0x3d80,0xbd18bd4e,0x3d753c95,0xbd713cac,0x3d0ebd55,0x3b493d80,0xbd22bd46,0x3d783c79,0xbd6d3cc4,0x3d04bd5c,0x3bc93d7f,0xbd2cbd3e,0x3d7b3c48,0xbd673cdb,0x3cf1bd62,0x3c163d7d,
0x3d0ebd55,0xbc163d7d,0xbc95bd75,0x3d2c3d3e,0x3d353d35,0xbd71bcac,0x3d7fbbc9,0xbd5c3d04,0xbc483d7b,0xbc79bd78,0x3d223d46,0xbd67bcdb,0xbd6dbcc4,0x3d80bb49,0xbd623cf1,0x3d18bd4e,
0x3d7bbc48,0xbd4e3d18,0x3cf1bd62,0xbb493d80,0x3d80,0xbcdbbd67,0x3d463d22,0xbd78bc79,0xbd553d0e,0x3d04bd5c,0xbbc93d7f,0xbcacbd71,0xbcc4bd6d,0x3d3e3d2c,0xbd75bc95,0x3d7dbc16,
0xbcc43d6d,0x3c16bd7d,0x3bc93d7f,0xbcacbd71,0x3d0e3d55,0xbd3ebd2c,0x3d623cf1,0xbd78bc79,0xbd35bd35,0x3d5c3d04,0xbd75bc95,0x3d803b49,0xbd7b3c48,0x3d67bcdb,0xbd463d22,0x3d18bd4e,
0x3d6dbcc4,0xbd4e3d18,0x3d22bd46,0xbcdb3d67,0x3c48bd7b,0x3b493d80,0xbc95bd75,0x3d043d5c,0x3d80,0xbc79bd78,0x3cf13d62,0xbd2cbd3e,0x3d553d0e,0xbd71bcac,0x3d7f3bc9,0xbd7d3c16,
0x3d7b3c48,0xbd7dbc16,0x3d7f3bc9,0xbd80bb49,0x3d6d3cc4,0xbd71bcac,0x3d753c95,0xbd78bc79,0x3d553d0e,0xbd5cbd04,0x3d623cf1,0xbd67bcdb,0x3d353d35,0xbd3ebd2c,0x3d463d22,0xbd4ebd18,
0x3d0e3d55,0xbd18bd4e,0x3d223d46,0xbd2cbd3e,0x3cc43d6d,0xbcdbbd67,0x3cf13d62,0xbd04bd5c,0x3c483d7b,0xbc79bd78,0x3c953d75,0xbcacbd71,0x3d80,0xbb49bd80,0x3bc93d7f,0xbc16bd7d,
0xbd800000,0x3c16bd7d,0x3d753c95,0xbcdb3d67,0xbd55bd0e,0x3d2cbd3e,0x3d223d46,0xbd5c3d04,0xbcc4bd6d,0x3d78bc79,0x3bc93d7f,0xbd80bb49,0x3c48bd7b,0x3d713cac,0xbcf13d62,0xbd4ebd18,
0x3d35bd35,0x3d183d4e,0xbd623cf1,0xbcacbd71,0x3d7bbc48,0x3b493d80,0xbd7fbbc9,0x3c79bd78,0x3d6d3cc4,0xbd043d5c,0xbd46bd22,0x3d3ebd2c,0x3d0e3d55,0xbd673cdb,0xbc95bd75,0x3d7dbc16,
0xbc48bd7b,0x3d7d3c16,0xbcf13d62,0xbd2cbd3e,0xbd800000,0x3cacbd71,0x3d463d22,0xbd5c3d04,0x3d0e3d55,0xbd783c79,0x3bc9bd7f,0x3d673cdb,0x3d6dbcc4,0x3b493d80,0xbd75bc95,0x3d18bd4e,
0xbd55bd0e,0x3d4ebd18,0x3c953d75,0xbd80bb49,0xbd353d35,0xbcdbbd67,0x3d7fbbc9,0xbc793d78,0x3d7b3c48,0xbd043d5c,0xbd22bd46,0x3d71bcac,0x3cc4bd6d,0x3d3e3d2c,0xbd623cf1,0xbc16bd7d,
0x3cc43d6d,0xbd7dbc16,0x3d22bd46,0x3cac3d71,0xbd7bbc48,0x3d2cbd3e,0x3c953d75,0xbd78bc79,0xbd800000,0x3d04bd5c,0x3cf13d62,0xbd80bb49,0x3d0ebd55,0x3cdb3d67,0xbd7fbbc9,0x3d18bd4e,
0xbd6dbcc4,0x3d4ebd18,0x3bc93d7f,0xbd67bcdb,0x3d55bd0e,0x3b493d80,0xbd62bcf1,0x3d5cbd04,0x3d35bd35,0x3c793d78,0xbd75bc95,0x3d3ebd2c,0x3c483d7b,0xbd71bcac,0x3d46bd22,0x3c163d7d,
0x3d55bd0e,0xbc163d7d,0xbd22bd46,0x3d803b49,0xbd6d3cc4,0x3cacbd71,0x3cf13d62,0xbd78bc79,0x3d7bbc48,0xbd043d5c,0xbc95bd75,0x3d673cdb,0xbd800000,0x3d2cbd3e,0x3bc93d7f,0xbd4ebd18,
0x3c48bd7b,0x3d183d4e,0xbd7fbbc9,0x3d3ebd2c,0xbcc43d6d,0xbcdbbd67,0x3d753c95,0xbd5c3d04,0x3d0ebd55,0x3c793d78,0xbd62bcf1,0x3d71bcac,0xbd353d35,0xbb49bd80,0x3d463d22,0xbd7d3c16,
0x3d35bd35,0xbc163d7d,0xbcf1bd62,0x3d673cdb,0xbd7b3c48,0x3d2cbd3e,0xbbc93d7f,0xbd04bd5c,0x3d6d3cc4,0xbd783c79,0x3d22bd46,0xbb493d80,0xbd0ebd55,0x3d713cac,0xbd753c95,0x3d18bd4e,
0xbd800000,0x3d4ebd18,0xbc953d75,0xbcacbd71,0x3d553d0e,0xbd803b49,0x3d46bd22,0xbc793d78,0xbcc4bd6d,0x3d5c3d04,0xbd7f3bc9,0x3d3ebd2c,0xbc483d7b,0xbcdbbd67,0x3d623cf1,0xbd7d3c16,
0x3d553d0e,0xbd7dbc16,0x3d75bc95,0xbd3e3d2c,0xbd353d35,0x3cacbd71,0x3bc93d7f,0xbd04bd5c,0xbd7bbc48,0x3d78bc79,0xbd463d22,0x3cdbbd67,0x3cc4bd6d,0x3b493d80,0xbcf1bd62,0x3d4e3d18,
0x3c483d7b,0xbd18bd4e,0x3d623cf1,0xbd80bb49,0xbd800000,0x3d67bcdb,0xbd223d46,0x3c79bd78,0xbd0ebd55,0x3d5c3d04,0xbd7fbbc9,0x3d71bcac,0x3d6dbcc4,0xbd2c3d3e,0x3c95bd75,0x3c163d7d,
0xbd6dbcc4,0x3d7d3c16,0xbd7f3bc9,0x3d71bcac,0xbd553d0e,0x3d2cbd3e,0xbcf13d62,0x3c79bd78,0x3d35bd35,0xbd043d5c,0x3c95bd75,0xbb493d80,0xbc48bd7b,0x3cdb3d67,0xbd22bd46,0x3d4e3d18,
0x3cc43d6d,0xbd18bd4e,0x3d463d22,0xbd67bcdb,0x3d7b3c48,0xbd803b49,0x3d75bc95,0xbd5c3d04,0xbd800000,0x3d78bc79,0xbd623cf1,0x3d3ebd2c,0xbd0e3d55,0x3cacbd71,0xbbc93d7f,0xbc16bd7d,
0xbc483d7b,0x3c16bd7d,0xbbc93d7f,0x3b49bd80,0xbcc43d6d,0x3cacbd71,0xbc953d75,0x3c79bd78,0xbd0e3d55,0x3d04bd5c,0xbcf13d62,0x3cdbbd67,0xbd353d35,0x3d2cbd3e,0xbd223d46,0x3d18bd4e,
0xbd553d0e,0x3d4ebd18,0xbd463d22,0x3d3ebd2c,0xbd6d3cc4,0x3d67bcdb,0xbd623cf1,0x3d5cbd04,0xbd7b3c48,0x3d78bc79,0xbd753c95,0x3d71bcac,0xbd800000,0x3d80bb49,0xbd7f3bc9,0x3d7dbc16,
0x3d80,0x3c16bd7d,0xbc953d75,0x3cdbbd67,0xbd0e3d55,0x3d2cbd3e,0xbd463d22,0x3d5cbd04,0xbd6d3cc4,0x3d78bc79,0xbd7f3bc9,0x3d803b49,0xbd7bbc48,0x3d713cac,0xbd62bcf1,0x3d4e3d18,
0xbd35bd35,0x3d183d4e,0xbcf1bd62,0x3cac3d71,0xbc48bd7b,0x3b493d80,0x3bc9bd7f,0xbc793d78,0x3cc4bd6d,0xbd043d5c,0x3d22bd46,0xbd3e3d2c,0x3d55bd0e,0xbd673cdb,0x3d75bc95,0xbd7d3c16,
0xbd7b3c48,0x3d7d3c16,0xbd62bcf1,0x3d2c3d3e,0x3d80,0x3cacbd71,0xbd223d46,0x3d5cbd04,0x3d55bd0e,0xbd783c79,0x3d7f3bc9,0xbd67bcdb,0xbcc4bd6d,0x3b493d80,0x3c95bd75,0xbd183d4e,
0xbd0e3d55,0x3d4ebd18,0xbd753c95,0x3d803b49,0x3d353d35,0xbcdbbd67,0x3bc93d7f,0x3c79bd78,0x3c48bd7b,0xbd043d5c,0x3d46bd22,0xbd713cac,0xbd6dbcc4,0x3d3e3d2c,0xbcf1bd62,0x3c163d7d,
0x3d6dbcc4,0xbd7dbc16,0x3d463d22,0xbcacbd71,0xbc483d7b,0x3d2cbd3e,0xbd753c95,0x3d783c79,0x3d80,0x3d04bd5c,0xbd623cf1,0x3d803b49,0xbd55bd0e,0x3cdb3d67,0x3bc9bd7f,0xbd183d4e,
0xbcc43d6d,0x3d4ebd18,0xbd7f3bc9,0x3d673cdb,0xbd0ebd55,0x3b493d80,0x3cf1bd62,0xbd5c3d04,0xbd35bd35,0x3c793d78,0x3c95bd75,0xbd3e3d2c,0x3d7bbc48,0xbd71bcac,0x3d223d46,0xbc16bd7d,
0xbd0ebd55,0xbc163d7d,0x3d46bd22,0xbd80bb49,0x3cc43d6d,0x3cacbd71,0xbd623cf1,0x3d783c79,0xbc48bd7b,0xbd043d5c,0x3d75bc95,0xbd67bcdb,0x3d80,0x3d2cbd3e,0xbd7f3bc9,0x3d4e3d18,
0xbd7bbc48,0x3d183d4e,0x3bc9bd7f,0xbd3e3d2c,0x3d6d3cc4,0xbcdbbd67,0xbc953d75,0x3d5cbd04,0xbd55bd0e,0x3c793d78,0x3cf1bd62,0xbd713cac,0x3d353d35,0xbb49bd80,0xbd223d46,0x3d7dbc16,
0xbd35bd35,0xbc163d7d,0x3d62bcf1,0xbd67bcdb,0x3c483d7b,0x3d2cbd3e,0xbd7fbbc9,0x3d043d5c,0x3cc4bd6d,0xbd783c79,0x3d463d22,0x3b49bd80,0xbd553d0e,0x3d713cac,0xbc95bd75,0xbd183d4e,
0x3d80,0x3d4ebd18,0xbd75bc95,0x3cac3d71,0x3d0ebd55,0xbd803b49,0x3d223d46,0x3c79bd78,0xbd6d3cc4,0x3d5c3d04,0xbbc9bd7f,0xbd3e3d2c,0x3d7b3c48,0xbcdbbd67,0xbcf13d62,0x3d7dbc16,
0x3d0ebd55,0xbd7dbc16,0x3c953d75,0x3d3ebd2c,0x3d353d35,0x3cacbd71,0xbd7f3bc9,0x3d043d5c,0xbc483d7b,0x3d78bc79,0xbd22bd46,0xbcdb3d67,0xbd6dbcc4,0x3b493d80,0x3d62bcf1,0xbd4ebd18,
0x3d7bbc48,0xbd18bd4e,0xbcf13d62,0x3d803b49,0x3d80,0x3d67bcdb,0xbd46bd22,0xbc793d78,0xbd553d0e,0x3d5c3d04,0x3bc9bd7f,0xbd713cac,0xbcc4bd6d,0xbd2c3d3e,0x3d753c95,0xbc16bd7d,
0xbcc43d6d,0x3d7d3c16,0xbbc9bd7f,0xbd713cac,0x3d0e3d55,0x3d2cbd3e,0xbd62bcf1,0xbc793d78,0xbd35bd35,0xbd043d5c,0x3d753c95,0x3b49bd80,0xbd7b3c48,0x3cdb3d67,0x3d46bd22,0xbd4ebd18,
0x3d6dbcc4,0xbd18bd4e,0xbd223d46,0x3d673cdb,0x3c48bd7b,0xbd803b49,0x3c953d75,0x3d5cbd04,0x3d80,0x3d78bc79,0xbcf1bd62,0xbd3e3d2c,0x3d553d0e,0x3cacbd71,0xbd7fbbc9,0x3c163d7d,
0x3d7b3c48,0x3c16bd7d,0xbd7fbbc9,0xbb493d80,0x3d6d3cc4,0x3cacbd71,0xbd75bc95,0xbc793d78,0x3d553d0e,0x3d04bd5c,0xbd62bcf1,0xbcdb3d67,0x3d353d35,0x3d2cbd3e,0xbd46bd22,0xbd183d4e,
0x3d0e3d55,0x3d4ebd18,0xbd22bd46,0xbd3e3d2c,0x3cc43d6d,0x3d67bcdb,0xbcf1bd62,0xbd5c3d04,0x3c483d7b,0x3d78bc79,0xbc95bd75,0xbd713cac,0x3d80,0x3d80bb49,0xbbc9bd7f,0xbd7d3c16,
0xbd800000,0x3d7d3c16,0xbd75bc95,0x3d673cdb,0xbd55bd0e,0x3d3e3d2c,0xbd22bd46,0x3d043d5c,0xbcc4bd6d,0x3c793d78,0xbbc9bd7f,0xbb493d80,0x3c48bd7b,0xbcac3d71,0x3cf1bd62,0xbd183d4e,
0x3d35bd35,0xbd4e3d18,0x3d62bcf1,0xbd713cac,0x3d7bbc48,0xbd803b49,0x3d7f3bc9,0xbd78bc79,0x3d6d3cc4,0xbd5cbd04,0x3d463d22,0xbd2cbd3e,0x3d0e3d55,0xbcdbbd67,0x3c953d75,0xbc16bd7d,
0xbc48bd7b,0xbc163d7d,0x3cf1bd62,0xbd3e3d2c,0xbd800000,0x3d713cac,0xbd46bd22,0x3d043d5c,0x3d0e3d55,0xbc79bd78,0xbbc93d7f,0x3cdbbd67,0x3d6dbcc4,0xbd803b49,0x3d753c95,0xbd4ebd18,
0xbd55bd0e,0x3d183d4e,0xbc95bd75,0xbb493d80,0xbd353d35,0x3d67bcdb,0xbd7f3bc9,0x3d783c79,0x3d7b3c48,0xbd5cbd04,0x3d223d46,0xbcacbd71,0x3cc4bd6d,0xbd2c3d3e,0x3d62bcf1,0xbd7d3c16,
0x3cc43d6d,0x3c16bd7d,0xbd223d46,0x3d71bcac,0xbd7bbc48,0x3d3e3d2c,0xbc95bd75,0xbc793d78,0xbd800000,0x3d5c3d04,0xbcf1bd62,0xbb493d80,0x3d0ebd55,0xbd673cdb,0x3d7f3bc9,0xbd4ebd18,
0xbd6dbcc4,0x3d183d4e,0xbbc9bd7f,0xbcdb3d67,0x3d55bd0e,0xbd803b49,0x3d623cf1,0xbd04bd5c,0x3d35bd35,0xbd783c79,0x3d753c95,0xbd2cbd3e,0x3c483d7b,0x3cacbd71,0xbd463d22,0x3d7dbc16,
0x3d55bd0e,0xbd7dbc16,0x3d223d46,0x3b49bd80,0xbd6d3cc4,0x3d713cac,0xbcf1bd62,0xbc793d78,0x3d7bbc48,0xbd5cbd04,0x3c953d75,0x3cdbbd67,0xbd800000,0x3d3e3d2c,0xbbc9bd7f,0xbd183d4e,
0x3c48bd7b,0xbd4e3d18,0x3d7f3bc9,0xbd2cbd3e,0xbcc43d6d,0x3d67bcdb,0xbd75bc95,0x3d043d5c,0x3d0ebd55,0xbd783c79,0x3d623cf1,0xbcacbd71,0xbd353d35,0x3d80bb49,0xbd46bd22,0x3c163d7d,
0x3d35bd35,0xbd7dbc16,0x3cf13d62,0x3cdbbd67,0xbd7b3c48,0x3d3e3d2c,0x3bc9bd7f,0xbd5c3d04,0x3d6d3cc4,0xbc79bd78,0xbd223d46,0x3d803b49,0xbd0ebd55,0xbcac3d71,0x3d75bc95,0xbd4ebd18,
0xbd800000,0x3d183d4e,0x3c95bd75,0xbd713cac,0x3d553d0e,0xbb49bd80,0xbd463d22,0x3d783c79,0xbcc4bd6d,0xbd043d5c,0x3d7fbbc9,0xbd2cbd3e,0xbc483d7b,0x3d67bcdb,0xbd62bcf1,0x3c163d7d,
0x3d553d0e,0x3c16bd7d,0xbd753c95,0x3d2c3d3e,0xbd353d35,0x3d713cac,0xbbc9bd7f,0xbd5c3d04,0xbd7bbc48,0x3c793d78,0x3d46bd22,0xbd67bcdb,0x3cc4bd6d,0xbd803b49,0x3cf13d62,0x3d18bd4e,
0x3c483d7b,0x3d4ebd18,0xbd62bcf1,0xbb493d80,0xbd800000,0x3cdb3d67,0x3d22bd46,0xbd78bc79,0xbd0ebd55,0xbd043d5c,0x3d7f3bc9,0xbcacbd71,0x3d6dbcc4,0xbd3ebd2c,0xbc953d75,0x3d7dbc16,
0xbd6dbcc4,0xbc163d7d,0x3d7fbbc9,0xbcacbd71,0xbd553d0e,0x3d3e3d2c,0x3cf1bd62,0xbd78bc79,0x3d35bd35,0xbd5cbd04,0xbc953d75,0x3d803b49,0xbc48bd7b,0xbd673cdb,0x3d223d46,0x3d18bd4e,
0x3cc43d6d,0x3d4ebd18,0xbd46bd22,0xbcdb3d67,0x3d7b3c48,0xbb49bd80,0xbd753c95,0x3d043d5c,0xbd800000,0x3c793d78,0x3d62bcf1,0xbd2cbd3e,0xbd0e3d55,0x3d713cac,0x3bc9bd7f,0xbd7d3c16,
0xbc483d7b,0x3d7d3c16,0x3bc9bd7f,0xbd80bb49,0xbcc43d6d,0x3d713cac,0x3c95bd75,0xbd78bc79,0xbd0e3d55,0x3d5c3d04,0x3cf1bd62,0xbd67bcdb,0xbd353d35,0x3d3e3d2c,0x3d22bd46,0xbd4ebd18,
0xbd553d0e,0x3d183d4e,0x3d46bd22,0xbd2cbd3e,0xbd6d3cc4,0x3cdb3d67,0x3d62bcf1,0xbd04bd5c,0xbd7b3c48,0x3c793d78,0x3d75bc95,0xbcacbd71,0xbd800000,0x3b493d80,0x3d7fbbc9,0xbc16bd7d,
0x3d80,0x3d7d3c16,0x3c95bd75,0xbd67bcdb,0xbd0e3d55,0x3d3e3d2c,0x3d46bd22,0xbd04bd5c,0xbd6d3cc4,0x3c793d78,0x3d7fbbc9,0x3b49bd80,0xbd7bbc48,0xbcac3d71,0x3d623cf1,0x3d18bd4e,
0xbd35bd35,0xbd4e3d18,0x3cf13d62,0x3d71bcac,0xbc48bd7b,0xbd803b49,0xbbc93d7f,0x3d783c79,0x3cc4bd6d,0xbd5cbd04,0xbd223d46,0x3d2c3d3e,0x3d55bd0e,0xbcdbbd67,0xbd753c95,0x3c163d7d,
0xbd7b3c48,0xbc163d7d,0x3d623cf1,0x3d3ebd2c,0x3d80,0x3d713cac,0x3d22bd46,0xbd04bd5c,0x3d55bd0e,0xbc79bd78,0xbd7fbbc9,0xbcdb3d67,0xbcc4bd6d,0xbd803b49,0xbc953d75,0x3d4e3d18,
0xbd0e3d55,0x3d183d4e,0x3d75bc95,0x3b49bd80,0x3d353d35,0x3d67bcdb,0xbbc9bd7f,0xbd78bc79,0x3c48bd7b,0xbd5cbd04,0xbd463d22,0x3cac3d71,0xbd6dbcc4,0xbd2c3d3e,0x3cf13d62,0x3d7dbc16,
0x3d6dbcc4,0x3c16bd7d,0xbd46bd22,0xbd713cac,0xbc483d7b,0x3d3e3d2c,0x3d75bc95,0x3c79bd78,0x3d80,0x3d5c3d04,0x3d62bcf1,0x3b49bd80,0xbd55bd0e,0xbd673cdb,0xbbc93d7f,0x3d4e3d18,
0xbcc43d6d,0x3d183d4e,0x3d7fbbc9,0x3cdbbd67,0xbd0ebd55,0xbd803b49,0xbcf13d62,0x3d043d5c,0xbd35bd35,0xbd783c79,0xbc953d75,0x3d2c3d3e,0x3d7bbc48,0x3cacbd71,0xbd22bd46,0xbd7d3c16,
0xbd0ebd55,0xbd7dbc16,0xbd463d22,0xbb493d80,0x3cc43d6d,0x3d713cac,0x3d62bcf1,0x3c79bd78,0xbc48bd7b,0xbd5cbd04,0xbd753c95,0xbcdb3d67,0x3d80,0x3d3e3d2c,0x3d7fbbc9,0x3d18bd4e,
0xbd7bbc48,0xbd4e3d18,0xbbc93d7f,0x3d2c3d3e,0x3d6d3cc4,0x3d67bcdb,0x3c95bd75,0xbd04bd5c,0xbd55bd0e,0xbd783c79,0xbcf13d62,0x3cac3d71,0x3d353d35,0x3d80bb49,0x3d22bd46,0xbc16bd7d,
0xbd35bd35,0xbd7dbc16,0xbd623cf1,0xbcdb3d67,0x3c483d7b,0x3d3e3d2c,0x3d7f3bc9,0x3d5cbd04,0x3cc4bd6d,0xbc79bd78,0xbd46bd22,0xbd80bb49,0xbd553d0e,0xbcac3d71,0x3c953d75,0x3d4e3d18,
0x3d80,0x3d183d4e,0x3d753c95,0x3d71bcac,0x3d0ebd55,0xbb49bd80,0xbd22bd46,0xbd78bc79,0xbd6d3cc4,0xbd043d5c,0x3bc93d7f,0x3d2c3d3e,0x3d7b3c48,0x3d67bcdb,0x3cf1bd62,0xbc16bd7d,
0x3d0ebd55,0x3c16bd7d,0xbc95bd75,0xbd2cbd3e,0x3d353d35,0x3d713cac,0x3d7fbbc9,0x3d5cbd04,0xbc483d7b,0x3c793d78,0x3d223d46,0x3d673cdb,0xbd6dbcc4,0xbd803b49,0xbd623cf1,0xbd183d4e,
0x3d7bbc48,0x3d4ebd18,0x3cf1bd62,0x3b49bd80,0x3d80,0x3cdb3d67,0x3d463d22,0x3d783c79,0xbd553d0e,0xbd043d5c,0xbbc93d7f,0x3cac3d71,0xbcc4bd6d,0xbd3ebd2c,0xbd75bc95,0xbd7d3c16,
0xbcc43d6d,0xbc163d7d,0x3bc93d7f,0x3cac3d71,0x3d0e3d55,0x3d3e3d2c,0x3d623cf1,0x3d783c79,0xbd35bd35,0xbd5cbd04,0xbd75bc95,0xbd80bb49,0xbd7b3c48,0xbd673cdb,0xbd463d22,0xbd183d4e,
0x3d6dbcc4,0x3d4ebd18,0x3d22bd46,0x3cdbbd67,0x3c48bd7b,0xbb49bd80,0xbc95bd75,0xbd04bd5c,0x3d80,0x3c793d78,0x3cf13d62,0x3d2c3d3e,0x3d553d0e,0x3d713cac,0x3d7f3bc9,0x3d7dbc16,
0x3d7b3c48,0x3d7d3c16,0x3d7f3bc9,0x3d803b49,0x3d6d3cc4,0x3d713cac,0x3d753c95,0x3d783c79,0x3d553d0e,0x3d5c3d04,0x3d623cf1,0x3d673cdb,0x3d353d35,0x3d3e3d2c,0x3d463d22,0x3d4e3d18,
0x3d0e3d55,0x3d183d4e,0x3d223d46,0x3d2c3d3e,0x3cc43d6d,0x3cdb3d67,0x3cf13d62,0x3d043d5c,0x3c483d7b,0x3c793d78,0x3c953d75,0x3cac3d71,0x3d80,0x3b493d80,0x3bc93d7f,0x3c163d7d,
0xbd800000,0xbc163d7d,0x3d753c95,0x3cdbbd67,0xbd55bd0e,0xbd2c3d3e,0x3d223d46,0x3d5cbd04,0xbcc4bd6d,0xbd783c79,0x3bc93d7f,0x3d803b49,0x3c48bd7b,0xbd71bcac,0xbcf13d62,0x3d4e3d18,
0x3d35bd35,0xbd18bd4e,0xbd623cf1,0x3cac3d71,0x3d7bbc48,0xbb49bd80,0xbd7fbbc9,0xbc793d78,0x3d6d3cc4,0x3d04bd5c,0xbd46bd22,0xbd3e3d2c,0x3d0e3d55,0x3d67bcdb,0xbc95bd75,0xbd7d3c16,
0xbc48bd7b,0xbd7dbc16,0xbcf13d62,0x3d2c3d3e,0xbd800000,0xbcac3d71,0x3d463d22,0x3d5cbd04,0x3d0e3d55,0x3d78bc79,0x3bc9bd7f,0xbd67bcdb,0x3d6dbcc4,0xbb49bd80,0xbd75bc95,0xbd183d4e,
0xbd55bd0e,0xbd4e3d18,0x3c953d75,0x3d803b49,0xbd353d35,0x3cdb3d67,0x3d7fbbc9,0x3c79bd78,0x3d7b3c48,0x3d04bd5c,0xbd22bd46,0xbd713cac,0x3cc4bd6d,0xbd3ebd2c,0xbd623cf1,0x3c163d7d,
0x3cc43d6d,0x3d7d3c16,0x3d22bd46,0xbcacbd71,0xbd7bbc48,0xbd2c3d3e,0x3c953d75,0x3d783c79,0xbd800000,0xbd043d5c,0x3cf13d62,0x3d803b49,0x3d0ebd55,0xbcdbbd67,0xbd7fbbc9,0xbd183d4e,
0xbd6dbcc4,0xbd4e3d18,0x3bc93d7f,0x3d673cdb,0x3d55bd0e,0xbb49bd80,0xbd62bcf1,0xbd5c3d04,0x3d35bd35,0xbc79bd78,0xbd75bc95,0xbd3e3d2c,0x3c483d7b,0x3d713cac,0x3d46bd22,0xbc16bd7d,
0x3d55bd0e,0x3c16bd7d,0xbd22bd46,0xbd80bb49,0xbd6d3cc4,0xbcac3d71,0x3cf13d62,0x3d783c79,0x3d7bbc48,0x3d04bd5c,0xbc95bd75,0xbd67bcdb,0xbd800000,0xbd2c3d3e,0x3bc93d7f,0x3d4e3d18,
0x3c48bd7b,0xbd18bd4e,0xbd7fbbc9,0xbd3e3d2c,0xbcc43d6d,0x3cdb3d67,0x3d753c95,0x3d5cbd04,0x3d0ebd55,0xbc79bd78,0xbd62bcf1,0xbd713cac,0xbd353d35,0x3b493d80,0x3d463d22,0x3d7dbc16,
0x3d35bd35,0x3c16bd7d,0xbcf1bd62,0xbd67bcdb,0xbd7b3c48,0xbd2c3d3e,0xbbc93d7f,0x3d043d5c,0x3d6d3cc4,0x3d78bc79,0x3d22bd46,0x3b49bd80,0xbd0ebd55,0xbd71bcac,0xbd753c95,0xbd183d4e,
0xbd800000,0xbd4e3d18,0xbc953d75,0x3cac3d71,0x3d553d0e,0x3d80bb49,0x3d46bd22,0x3c79bd78,0xbcc4bd6d,0xbd5cbd04,0xbd7f3bc9,0xbd3e3d2c,0xbc483d7b,0x3cdb3d67,0x3d623cf1,0x3d7dbc16,
0x3d553d0e,0x3d7d3c16,0x3d75bc95,0x3d3ebd2c,0xbd353d35,0xbcac3d71,0x3bc93d7f,0x3d043d5c,0xbd7bbc48,0xbd783c79,0xbd463d22,0xbcdb3d67,0x3cc4bd6d,0xbb49bd80,0xbcf1bd62,0xbd4ebd18,
0x3c483d7b,0x3d183d4e,0x3d623cf1,0x3d803b49,0xbd800000,0xbd673cdb,0xbd223d46,0xbc793d78,0xbd0ebd55,0xbd5cbd04,0xbd7fbbc9,0xbd713cac,0x3d6dbcc4,0x3d2cbd3e,0x3c95bd75,0xbc16bd7d,
0xbd6dbcc4,0xbd7dbc16,0xbd7f3bc9,0xbd713cac,0xbd553d0e,0xbd2c3d3e,0xbcf13d62,0xbc793d78,0x3d35bd35,0x3d04bd5c,0x3c95bd75,0x3b49bd80,0xbc48bd7b,0xbcdbbd67,0xbd22bd46,0xbd4ebd18,
0x3cc43d6d,0x3d183d4e,0x3d463d22,0x3d673cdb,0x3d7b3c48,0x3d80bb49,0x3d75bc95,0x3d5cbd04,0xbd800000,0xbd783c79,0xbd623cf1,0xbd3e3d2c,0xbd0e3d55,0xbcac3d71,0xbbc93d7f,0x3c163d7d,
0xbc483d7b,0xbc163d7d,0xbbc93d7f,0xbb493d80,0xbcc43d6d,0xbcac3d71,0xbc953d75,0xbc793d78,0xbd0e3d55,0xbd043d5c,0xbcf13d62,0xbcdb3d67,0xbd353d35,0xbd2c3d3e,0xbd223d46,0xbd183d4e,
0xbd553d0e,0xbd4e3d18,0xbd463d22,0xbd3e3d2c,0xbd6d3cc4,0xbd673cdb,0xbd623cf1,0xbd5c3d04,0xbd7b3c48,0xbd783c79,0xbd753c95,0xbd713cac,0xbd800000,0xbd803b49,0xbd7f3bc9,0xbd7d3c16,
0x3f003f00,0xbf003f00,0x3f003f00,0xbf003f00,0x3f003f00,0xbf003f00,0x3f003f00,0xbf003f00,0x3f003f00,0xbf003f00,0x3f003f00,0xbf003f00,0x3f003f00,0xbf003f00,0x3f003f00,0xbf003f00,
0x3eff3f00,0xbd490000,0x3ea23eb5,0xbec6beb5,0x3ef53efb,0xbe15bdc8,0x3e713e8e,0xbee2bed5,0x3ee23eed,0xbe71be44,0x3e153e44,0xbef5beed,0x3ec63ed5,0xbea2be8e,0x3d493dc8,0xbeffbefb,
0x3efb3f00,0xbdc80000,0xbdc80000,0xbefbbf00,0x3ed53eed,0xbe8ebe44,0xbe8ebe44,0xbed5beed,0x3e8e3eb5,0xbed5beb5,0xbed5beb5,0xbe8ebeb5,0x3dc83e44,0xbefbbeed,0xbefbbeed,0xbdc8be44,
0x3ef53f00,0xbe150000,0xbee2beb5,0xbe71beb5,0x3ea23ed5,0xbec6be8e,0xbeffbefb,0x3d49bdc8,0x3d493e44,0xbeffbeed,0xbec6beed,0x3ea23e44,0xbe71bdc8,0xbee2befb,0xbe15be8e,0x3ef53ed5,
0x3eed3f00,0xbe440000,0xbeedbf00,0x3e440000,0x3e443eb5,0xbeedbeb5,0xbe44beb5,0x3eed3eb5,0xbe440000,0xbeedbf00,0x3e440000,0x3eed3f00,0xbeedbeb5,0xbe44beb5,0x3eed3eb5,0x3e443eb5,
0x3ee23f00,0xbe710000,0xbe15beb5,0x3ef53eb5,0x3d493e8e,0xbeffbed5,0x3ea23dc8,0x3ec63efb,0xbec6be44,0xbea2beed,0x3eff3eed,0xbd493e44,0xbef5befb,0x3e15bdc8,0x3e713ed5,0xbee2be8e,
0x3ed53f00,0xbe8e0000,0x3e8e0000,0x3ed53f00,0xbdc83e44,0xbefbbeed,0x3efb3eed,0xbdc83e44,0xbefbbeb5,0xbdc8beb5,0x3dc83eb5,0xbefbbeb5,0xbe8ebeed,0x3ed53e44,0xbed5be44,0xbe8ebeed,
0x3ec63f00,0xbea20000,0x3eff3eb5,0x3d493eb5,0xbe713dc8,0xbee2befb,0x3e153ed5,0xbef5be8e,0xbef5beed,0x3e15be44,0xbee2be44,0xbe71beed,0x3d49be8e,0x3eff3ed5,0xbea2befb,0x3ec63dc8,
0x3f00,0xbf000000,0x3f00,0xbf000000,0xbf00,0x3f000000,0xbf00,0x3f000000,0x3f00,0xbf000000,0x3f00,0xbf000000,0xbf00,0x3f000000,0xbf00,0x3f000000,
0xbd493f00,0xbeff0000,0xbec63eb5,0xbea2beb5,0x3e15befb,0x3ef53dc8,0x3ee2be8e,0x3e713ed5,0xbe713eed,0xbee2be44,0xbef53e44,0xbe15beed,0x3ea2bed5,0x3ec63e8e,0x3effbdc8,0x3d493efb,
0xbdc83f00,0xbefb0000,0xbefb0000,0x3dc8bf00,0x3e8ebeed,0x3ed53e44,0x3ed53e44,0xbe8e3eed,0xbed53eb5,0xbe8ebeb5,0xbe8ebeb5,0x3ed5beb5,0x3efbbe44,0x3dc83eed,0x3dc83eed,0xbefb3e44,
0xbe153f00,0xbef50000,0xbe71beb5,0x3ee2beb5,0x3ec6bed5,0x3ea23e8e,0xbd493efb,0xbeff3dc8,0xbeff3e44,0xbd49beed,0x3ea2beed,0x3ec63e44,0x3ee23dc8,0xbe713efb,0xbef53e8e,0xbe15bed5,
0xbe443f00,0xbeed0000,0x3e44bf00,0x3eed0000,0x3eedbeb5,0x3e443eb5,0xbeed3eb5,0xbe44beb5,0xbeed0000,0x3e44bf00,0x3eed0000,0xbe443f00,0x3e443eb5,0xbeed3eb5,0xbe44beb5,0x3eedbeb5,
0xbe713f00,0xbee20000,0x3ef5beb5,0x3e153eb5,0x3effbe8e,0x3d493ed5,0xbec6bdc8,0x3ea2befb,0xbea2be44,0x3ec6beed,0xbd493eed,0xbeff3e44,0xbe153efb,0xbef53dc8,0x3ee2bed5,0x3e713e8e,
0xbe8e3f00,0xbed50000,0x3ed50000,0xbe8e3f00,0x3efbbe44,0xbdc83eed,0x3dc8beed,0x3efbbe44,0xbdc8beb5,0x3efbbeb5,0xbefb3eb5,0xbdc8beb5,0xbed53eed,0xbe8ebe44,0x3e8e3e44,0xbed53eed,
0xbea23f00,0xbec60000,0x3d493eb5,0xbeff3eb5,0x3ee2bdc8,0xbe713efb,0x3ef5bed5,0x3e153e8e,0x3e15beed,0x3ef5be44,0xbe71be44,0x3ee2beed,0xbeff3e8e,0x3d49bed5,0xbec63efb,0xbea2bdc8,
0x3eb53f00,0xbeb50000,0x3eb53f00,0xbeb50000,0xbeb50000,0xbeb5bf00,0xbeb50000,0xbeb5bf00,0xbeb5bf00,0x3eb50000,0xbeb5bf00,0x3eb50000,0x3eb50000,0x3eb53f00,0x3eb50000,0x3eb53f00,
0xbeff3f00,0x3d490000,0xbea23eb5,0x3ec6beb5,0xbef53efb,0x3e15bdc8,0xbe713e8e,0x3ee2bed5,0xbee23eed,0x3e71be44,0xbe153e44,0x3ef5beed,0xbec63ed5,0x3ea2be8e,0xbd493dc8,0x3effbefb,
0xbefb3f00,0x3dc80000,0x3dc80000,0x3efbbf00,0xbed53eed,0x3e8ebe44,0x3e8ebe44,0x3ed5beed,0xbe8e3eb5,0x3ed5beb5,0x3ed5beb5,0x3e8ebeb5,0xbdc83e44,0x3efbbeed,0x3efbbeed,0x3dc8be44,
0xbef53f00,0x3e150000,0x3ee2beb5,0x3e71beb5,0xbea23ed5,0x3ec6be8e,0x3effbefb,0xbd49bdc8,0xbd493e44,0x3effbeed,0x3ec6beed,0xbea23e44,0x3e71bdc8,0x3ee2befb,0x3e15be8e,0xbef53ed5,
0xbeed3f00,0x3e440000,0x3eedbf00,0xbe440000,0xbe443eb5,0x3eedbeb5,0x3e44beb5,0xbeed3eb5,0x3e440000,0x3eedbf00,0xbe440000,0xbeed3f00,0x3eedbeb5,0x3e44beb5,0xbeed3eb5,0xbe443eb5,
0xbee23f00,0x3e710000,0x3e15beb5,0xbef53eb5,0xbd493e8e,0x3effbed5,0xbea23dc8,0xbec63efb,0x3ec6be44,0x3ea2beed,0xbeff3eed,0x3d493e44,0x3ef5befb,0xbe15bdc8,0xbe713ed5,0x3ee2be8e,
0xbed53f00,0x3e8e0000,0xbe8e0000,0xbed53f00,0x3dc83e44,0x3efbbeed,0xbefb3eed,0x3dc83e44,0x3efbbeb5,0x3dc8beb5,0xbdc83eb5,0x3efbbeb5,0x3e8ebeed,0xbed53e44,0x3ed5be44,0x3e8ebeed,
0xbec63f00,0x3ea20000,0xbeff3eb5,0xbd493eb5,0x3e713dc8,0x3ee2befb,0xbe153ed5,0x3ef5be8e,0x3ef5beed,0xbe15be44,0x3ee2be44,0x3e71beed,0xbd49be8e,0xbeff3ed5,0x3ea2befb,0xbec63dc8,
0xbeb53f00,0xbeb50000,0xbeb53f00,0xbeb50000,0x3eb50000,0xbeb53f00,0x3eb50000,0xbeb53f00,0x3eb5bf00,0x3eb50000,0x3eb5bf00,0x3eb50000,0xbeb50000,0x3eb5bf00,0xbeb50000,0x3eb5bf00,
0x3d493f00,0x3eff0000,0x3ec63eb5,0x3ea2beb5,0xbe15befb,0xbef53dc8,0xbee2be8e,0xbe713ed5,0x3e713eed,0x3ee2be44,0x3ef53e44,0x3e15beed,0xbea2bed5,0xbec63e8e,0xbeffbdc8,0xbd493efb,
0x3dc83f00,0x3efb0000,0x3efb0000,0xbdc8bf00,0xbe8ebeed,0xbed53e44,0xbed53e44,0x3e8e3eed,0x3ed53eb5,0x3e8ebeb5,0x3e8ebeb5,0xbed5beb5,0xbefbbe44,0xbdc83eed,0xbdc83eed,0x3efb3e44,
0x3e153f00,0x3ef50000,0x3e71beb5,0xbee2beb5,0xbec6bed5,0xbea23e8e,0x3d493efb,0x3eff3dc8,0x3eff3e44,0x3d49beed,0xbea2beed,0xbec63e44,0xbee23dc8,0x3e713efb,0x3ef53e8e,0x3e15bed5,
0x3e443f00,0x3eed0000,0xbe44bf00,0xbeed0000,0xbeedbeb5,0xbe443eb5,0x3eed3eb5,0x3e44beb5,0x3eed0000,0xbe44bf00,0xbeed0000,0x3e443f00,0xbe443eb5,0x3eed3eb5,0x3e44beb5,0xbeedbeb5,
0x3e713f00,0x3ee20000,0xbef5beb5,0xbe153eb5,0xbeffbe8e,0xbd493ed5,0x3ec6bdc8,0xbea2befb,0x3ea2be44,0xbec6beed,0x3d493eed,0x3eff3e44,0x3e153efb,0x3ef53dc8,0xbee2bed5,0xbe713e8e,
0x3e8e3f00,0x3ed50000,0xbed50000,0x3e8e3f00,0xbefbbe44,0x3dc83eed,0xbdc8beed,0xbefbbe44,0x3dc8beb5,0xbefbbeb5,0x3efb3eb5,0x3dc8beb5,0x3ed53eed,0x3e8ebe44,0xbe8e3e44,0x3ed53eed,
0x3ea23f00,0x3ec60000,0xbd493eb5,0x3eff3eb5,0xbee2bdc8,0x3e713efb,0xbef5bed5,0xbe153e8e,0xbe15beed,0xbef5be44,0x3e71be44,0xbee2beed,0x3eff3e8e,0xbd49bed5,0x3ec63efb,0x3ea2bdc8,
0x3f003f00,0xbf003f00,0x3f003f00,0xbf003f00,0x3f003f00,0xbf003f00,0x3f003f00,0xbf003f00,0x3f003f00,0xbf003f00,0x3f003f00,0xbf003f00,0x3f003f00,0xbf003f00,0x3f003f00,0xbf003f00,
0xbd490000,0xbeffbf00,0xbec6beb5,0xbea2beb5,0xbe15bdc8,0xbef5befb,0xbee2bed5,0xbe71be8e,0xbe71be44,0xbee2beed,0xbef5beed,0xbe15be44,0xbea2be8e,0xbec6bed5,0xbeffbefb,0xbd49bdc8,
0xbefbbf00,0x3dc80000,0x3dc80000,0x3efb3f00,0xbed5beed,0x3e8e3e44,0x3e8e3e44,0x3ed53eed,0xbe8ebeb5,0x3ed53eb5,0x3ed53eb5,0x3e8e3eb5,0xbdc8be44,0x3efb3eed,0x3efb3eed,0x3dc83e44,
0x3e150000,0x3ef53f00,0x3e713eb5,0xbee2beb5,0x3ec63e8e,0x3ea23ed5,0xbd493dc8,0xbeffbefb,0x3eff3eed,0x3d493e44,0xbea2be44,0xbec6beed,0x3ee23efb,0xbe71bdc8,0xbef5bed5,0xbe15be8e,
0x3eed3f00,0xbe440000,0xbeedbf00,0x3e440000,0x3e443eb5,0xbeedbeb5,0xbe44beb5,0x3eed3eb5,0xbe440000,0xbeedbf00,0x3e440000,0x3eed3f00,0xbeedbeb5,0xbe44beb5,0x3eed3eb5,0x3e443eb5,
0xbe710000,0xbee2bf00,0x3ef53eb5,0x3e153eb5,0xbeffbed5,0xbd49be8e,0x3ec63efb,0xbea2bdc8,0xbea2beed,0x3ec63e44,0xbd493e44,0xbeffbeed,0x3e15bdc8,0x3ef53efb,0xbee2be8e,0xbe71bed5,
0xbed5bf00,0x3e8e0000,0xbe8e0000,0xbed5bf00,0x3dc8be44,0x3efb3eed,0xbefbbeed,0x3dc8be44,0x3efb3eb5,0x3dc83eb5,0xbdc8beb5,0x3efb3eb5,0x3e8e3eed,0xbed5be44,0x3ed53e44,0x3e8e3eed,
0x3ea20000,0x3ec63f00,0xbd49beb5,0x3eff3eb5,0x3ee23efb,0xbe713dc8,0x3ef53e8e,0x3e153ed5,0xbe153e44,0xbef5beed,0x3e713eed,0xbee2be44,0xbeffbed5,0x3d49be8e,0xbec6bdc8,0xbea2befb,
0x3f00,0xbf000000,0x3f00,0xbf000000,0xbf00,0x3f000000,0xbf00,0x3f000000,0x3f00,0xbf000000,0x3f00,0xbf000000,0xbf00,0x3f000000,0xbf00,0x3f000000,
0xbeff0000,0x3d49bf00,0xbea2beb5,0x3ec6beb5,0x3ef53dc8,0xbe153efb,0x3e713ed5,0xbee23e8e,0xbee2be44,0x3e71beed,0xbe15beed,0x3ef5be44,0x3ec63e8e,0xbea23ed5,0x3d493efb,0xbeff3dc8,
0x3dc8bf00,0x3efb0000,0x3efb0000,0xbdc83f00,0xbe8e3eed,0xbed5be44,0xbed5be44,0x3e8ebeed,0x3ed5beb5,0x3e8e3eb5,0x3e8e3eb5,0xbed53eb5,0xbefb3e44,0xbdc8beed,0xbdc8beed,0x3efbbe44,
0x3ef50000,0xbe153f00,0xbee23eb5,0xbe71beb5,0xbea2be8e,0x3ec6bed5,0x3effbdc8,0xbd493efb,0x3d493eed,0xbeff3e44,0xbec6be44,0x3ea2beed,0x3e71befb,0x3ee23dc8,0x3e153ed5,0xbef53e8e,
0xbe443f00,0xbeed0000,0x3e44bf00,0x3eed0000,0x3eedbeb5,0x3e443eb5,0xbeed3eb5,0xbe44beb5,0xbeed0000,0x3e44bf00,0x3eed0000,0xbe443f00,0x3e443eb5,0xbeed3eb5,0xbe44beb5,0x3eedbeb5,
0xbee20000,0x3e71bf00,0x3e153eb5,0xbef53eb5,0x3d493ed5,0xbeff3e8e,0x3ea2befb,0x3ec63dc8,0x3ec6beed,0x3ea23e44,0xbeff3e44,0x3d49beed,0xbef53dc8,0x3e15befb,0x3e713e8e,0xbee23ed5,
0x3e8ebf00,0x3ed50000,0xbed50000,0x3e8ebf00,0xbefb3e44,0x3dc8beed,0xbdc83eed,0xbefb3e44,0x3dc83eb5,0xbefb3eb5,0x3efbbeb5,0x3dc83eb5,0x3ed5beed,0x3e8e3e44,0xbe8ebe44,0x3ed5beed,
0x3ec60000,0xbea23f00,0x3effbeb5,0x3d493eb5,0x3e71befb,0x3ee2bdc8,0xbe15be8e,0x3ef5bed5,0xbef53e44,0x3e15beed,0xbee23eed,0xbe71be44,0xbd493ed5,0xbeff3e8e,0x3ea23dc8,0xbec63efb,
0x3eb53f00,0xbeb50000,0x3eb53f00,0xbeb50000,0xbeb50000,0xbeb5bf00,0xbeb50000,0xbeb5bf00,0xbeb5bf00,0x3eb50000,0xbeb5bf00,0x3eb50000,0x3eb50000,0x3eb53f00,0x3eb50000,0x3eb53f00,
0x3d490000,0x3effbf00,0x3ec6beb5,0x3ea2beb5,0x3e15bdc8,0x3ef5befb,0x3ee2bed5,0x3e71be8e,0x3e71be44,0x3ee2beed,0x3ef5beed,0x3e15be44,0x3ea2be8e,0x3ec6bed5,0x3effbefb,0x3d49bdc8,
0x3efbbf00,0xbdc80000,0xbdc80000,0xbefb3f00,0x3ed5beed,0xbe8e3e44,0xbe8e3e44,0xbed53eed,0x3e8ebeb5,0xbed53eb5,0xbed53eb5,0xbe8e3eb5,0x3dc8be44,0xbefb3eed,0xbefb3eed,0xbdc83e44,
0xbe150000,0xbef53f00,0xbe713eb5,0x3ee2beb5,0xbec63e8e,0xbea23ed5,0x3d493dc8,0x3effbefb,0xbeff3eed,0xbd493e44,0x3ea2be44,0x3ec6beed,0xbee23efb,0x3e71bdc8,0x3ef5bed5,0x3e15be8e,
0xbeed3f00,0x3e440000,0x3eedbf00,0xbe440000,0xbe443eb5,0x3eedbeb5,0x3e44beb5,0xbeed3eb5,0x3e440000,0x3eedbf00,0xbe440000,0xbeed3f00,0x3eedbeb5,0x3e44beb5,0xbeed3eb5,0xbe443eb5,
0x3e710000,0x3ee2bf00,0xbef53eb5,0xbe153eb5,0x3effbed5,0x3d49be8e,0xbec63efb,0x3ea2bdc8,0x3ea2beed,0xbec63e44,0x3d493e44,0x3effbeed,0xbe15bdc8,0xbef53efb,0x3ee2be8e,0x3e71bed5,
0x3ed5bf00,0xbe8e0000,0x3e8e0000,0x3ed5bf00,0xbdc8be44,0xbefb3eed,0x3efbbeed,0xbdc8be44,0xbefb3eb5,0xbdc83eb5,0x3dc8beb5,0xbefb3eb5,0xbe8e3eed,0x3ed5be44,0xbed53e44,0xbe8e3eed,
0xbea20000,0xbec63f00,0x3d49beb5,0xbeff3eb5,0xbee23efb,0x3e713dc8,0xbef53e8e,0xbe153ed5,0x3e153e44,0x3ef5beed,0xbe713eed,0x3ee2be44,0x3effbed5,0xbd49be8e,0x3ec6bdc8,0x3ea2befb,
0xbeb53f00,0xbeb50000,0xbeb53f00,0xbeb50000,0x3eb50000,0xbeb53f00,0x3eb50000,0xbeb53f00,0x3eb5bf00,0x3eb50000,0x3eb5bf00,0x3eb50000,0xbeb50000,0x3eb5bf00,0xbeb50000,0x3eb5bf00,
0x3eff0000,0xbd49bf00,0x3ea2beb5,0xbec6beb5,0xbef53dc8,0x3e153efb,0xbe713ed5,0x3ee23e8e,0x3ee2be44,0xbe71beed,0x3e15beed,0xbef5be44,0xbec63e8e,0x3ea23ed5,0xbd493efb,0x3eff3dc8,
0xbdc8bf00,0xbefb0000,0xbefb0000,0x3dc83f00,0x3e8e3eed,0x3ed5be44,0x3ed5be44,0xbe8ebeed,0xbed5beb5,0xbe8e3eb5,0xbe8e3eb5,0x3ed53eb5,0x3efb3e44,0x3dc8beed,0x3dc8beed,0xbefbbe44,
0xbef50000,0x3e153f00,0x3ee23eb5,0x3e71beb5,0x3ea2be8e,0xbec6bed5,0xbeffbdc8,0x3d493efb,0xbd493eed,0x3eff3e44,0x3ec6be44,0xbea2beed,0xbe71befb,0xbee23dc8,0xbe153ed5,0x3ef53e8e,
0x3e443f00,0x3eed0000,0xbe44bf00,0xbeed0000,0xbeedbeb5,0xbe443eb5,0x3eed3eb5,0x3e44beb5,0x3eed0000,0xbe44bf00,0xbeed0000,0x3e443f00,0xbe443eb5,0x3eed3eb5,0x3e44beb5,0xbeedbeb5,
0x3ee20000,0xbe71bf00,0xbe153eb5,0x3ef53eb5,0xbd493ed5,0x3eff3e8e,0xbea2befb,0xbec63dc8,0xbec6beed,0xbea23e44,0x3eff3e44,0xbd49beed,0x3ef53dc8,0xbe15befb,0xbe713e8e,0x3ee23ed5,
0xbe8ebf00,0xbed50000,0x3ed50000,0xbe8ebf00,0x3efb3e44,0xbdc8beed,0x3dc83eed,0x3efb3e44,0xbdc83eb5,0x3efb3eb5,0xbefbbeb5,0xbdc83eb5,0xbed5beed,0xbe8e3e44,0x3e8ebe44,0xbed5beed,
0xbec60000,0x3ea23f00,0xbeffbeb5,0xbd493eb5,0xbe71befb,0xbee2bdc8,0x3e15be8e,0xbef5bed5,0x3ef53e44,0xbe15beed,0x3ee23eed,0x3e71be44,0x3d493ed5,0x3eff3e8e,0xbea23dc8,0x3ec63efb,
0x3f003f00,0xbf003f00,0x3f003f00,0xbf003f00,0x3f003f00,0xbf003f00,0x3f003f00,0xbf003f00,0x3f003f00,0xbf003f00,0x3f003f00,0xbf003f00,0x3f003f00,0xbf003f00,0x3f003f00,0xbf003f00,
0xbeffbf00,0x3d490000,0xbea2beb5,0x3ec63eb5,0xbef5befb,0x3e153dc8,0xbe71be8e,0x3ee23ed5,0xbee2beed,0x3e713e44,0xbe15be44,0x3ef53eed,0xbec6bed5,0x3ea23e8e,0xbd49bdc8,0x3eff3efb,
0x3efb3f00,0xbdc80000,0xbdc80000,0xbefbbf00,0x3ed53eed,0xbe8ebe44,0xbe8ebe44,0xbed5beed,0x3e8e3eb5,0xbed5beb5,0xbed5beb5,0xbe8ebeb5,0x3dc83e44,0xbefbbeed,0xbefbbeed,0xbdc8be44,
0xbef5bf00,0x3e150000,0x3ee23eb5,0x3e713eb5,0xbea2bed5,0x3ec63e8e,0x3eff3efb,0xbd493dc8,0xbd49be44,0x3eff3eed,0x3ec63eed,0xbea2be44,0x3e713dc8,0x3ee23efb,0x3e153e8e,0xbef5bed5,
0x3eed3f00,0xbe440000,0xbeedbf00,0x3e440000,0x3e443eb5,0xbeedbeb5,0xbe44beb5,0x3eed3eb5,0xbe440000,0xbeedbf00,0x3e440000,0x3eed3f00,0xbeedbeb5,0xbe44beb5,0x3eed3eb5,0x3e443eb5,
0xbee2bf00,0x3e710000,0x3e153eb5,0xbef5beb5,0xbd49be8e,0x3eff3ed5,0xbea2bdc8,0xbec6befb,0x3ec63e44,0x3ea23eed,0xbeffbeed,0x3d49be44,0x3ef53efb,0xbe153dc8,0xbe71bed5,0x3ee23e8e,
0x3ed53f00,0xbe8e0000,0x3e8e0000,0x3ed53f00,0xbdc83e44,0xbefbbeed,0x3efb3eed,0xbdc83e44,0xbefbbeb5,0xbdc8beb5,0x3dc83eb5,0xbefbbeb5,0xbe8ebeed,0x3ed53e44,0xbed5be44,0xbe8ebeed,
0xbec6bf00,0x3ea20000,0xbeffbeb5,0xbd49beb5,0x3e71bdc8,0x3ee23efb,0xbe15bed5,0x3ef53e8e,0x3ef53eed,0xbe153e44,0x3ee23e44,0x3e713eed,0xbd493e8e,0xbeffbed5,0x3ea23efb,0xbec6bdc8,
0x3f00,0xbf000000,0x3f00,0xbf000000,0xbf00,0x3f000000,0xbf00,0x3f000000,0x3f00,0xbf000000,0x3f00,0xbf000000,0xbf00,0x3f000000,0xbf00,0x3f000000,
0x3d49bf00,0x3eff0000,0x3ec6beb5,0x3ea23eb5,0xbe153efb,0xbef5bdc8,0xbee23e8e,0xbe71bed5,0x3e71beed,0x3ee23e44,0x3ef5be44,0x3e153eed,0xbea23ed5,0xbec6be8e,0xbeff3dc8,0xbd49befb,
0xbdc83f00,0xbefb0000,0xbefb0000,0x3dc8bf00,0x3e8ebeed,0x3ed53e44,0x3ed53e44,0xbe8e3eed,0xbed53eb5,0xbe8ebeb5,0xbe8ebeb5,0x3ed5beb5,0x3efbbe44,0x3dc83eed,0x3dc83eed,0xbefb3e44,
0x3e15bf00,0x3ef50000,0x3e713eb5,0xbee23eb5,0xbec63ed5,0xbea2be8e,0x3d49befb,0x3effbdc8,0x3effbe44,0x3d493eed,0xbea23eed,0xbec6be44,0xbee2bdc8,0x3e71befb,0x3ef5be8e,0x3e153ed5,
0xbe443f00,0xbeed0000,0x3e44bf00,0x3eed0000,0x3eedbeb5,0x3e443eb5,0xbeed3eb5,0xbe44beb5,0xbeed0000,0x3e44bf00,0x3eed0000,0xbe443f00,0x3e443eb5,0xbeed3eb5,0xbe44beb5,0x3eedbeb5,
0x3e71bf00,0x3ee20000,0xbef53eb5,0xbe15beb5,0xbeff3e8e,0xbd49bed5,0x3ec63dc8,0xbea23efb,0x3ea23e44,0xbec63eed,0x3d49beed,0x3effbe44,0x3e15befb,0x3ef5bdc8,0xbee23ed5,0xbe71be8e,
0xbe8e3f00,0xbed50000,0x3ed50000,0xbe8e3f00,0x3efbbe44,0xbdc83eed,0x3dc8beed,0x3efbbe44,0xbdc8beb5,0x3efbbeb5,0xbefb3eb5,0xbdc8beb5,0xbed53eed,0xbe8ebe44,0x3e8e3e44,0xbed53eed,
0x3ea2bf00,0x3ec60000,0xbd49beb5,0x3effbeb5,0xbee23dc8,0x3e71befb,0xbef53ed5,0xbe15be8e,0xbe153eed,0xbef53e44,0x3e713e44,0xbee23eed,0x3effbe8e,0xbd493ed5,0x3ec6befb,0x3ea23dc8,
0x3eb53f00,0xbeb50000,0x3eb53f00,0xbeb50000,0xbeb50000,0xbeb5bf00,0xbeb50000,0xbeb5bf00,0xbeb5bf00,0x3eb50000,0xbeb5bf00,0x3eb50000,0x3eb50000,0x3eb53f00,0x3eb50000,0x3eb53f00,
0x3effbf00,0xbd490000,0x3ea2beb5,0xbec63eb5,0x3ef5befb,0xbe153dc8,0x3e71be8e,0xbee23ed5,0x3ee2beed,0xbe713e44,0x3e15be44,0xbef53eed,0x3ec6bed5,0xbea23e8e,0x3d49bdc8,0xbeff3efb,
0xbefb3f00,0x3dc80000,0x3dc80000,0x3efbbf00,0xbed53eed,0x3e8ebe44,0x3e8ebe44,0x3ed5beed,0xbe8e3eb5,0x3ed5beb5,0x3ed5beb5,0x3e8ebeb5,0xbdc83e44,0x3efbbeed,0x3efbbeed,0x3dc8be44,
0x3ef5bf00,0xbe150000,0xbee23eb5,0xbe713eb5,0x3ea2bed5,0xbec63e8e,0xbeff3efb,0x3d493dc8,0x3d49be44,0xbeff3eed,0xbec63eed,0x3ea2be44,0xbe713dc8,0xbee23efb,0xbe153e8e,0x3ef5bed5,
0xbeed3f00,0x3e440000,0x3eedbf00,0xbe440000,0xbe443eb5,0x3eedbeb5,0x3e44beb5,0xbeed3eb5,0x3e440000,0x3eedbf00,0xbe440000,0xbeed3f00,0x3eedbeb5,0x3e44beb5,0xbeed3eb5,0xbe443eb5,
0x3ee2bf00,0xbe710000,0xbe153eb5,0x3ef5beb5,0x3d49be8e,0xbeff3ed5,0x3ea2bdc8,0x3ec6befb,0xbec63e44,0xbea23eed,0x3effbeed,0xbd49be44,0xbef53efb,0x3e153dc8,0x3e71bed5,0xbee23e8e,
0xbed53f00,0x3e8e0000,0xbe8e0000,0xbed53f00,0x3dc83e44,0x3efbbeed,0xbefb3eed,0x3dc83e44,0x3efbbeb5,0x3dc8beb5,0xbdc83eb5,0x3efbbeb5,0x3e8ebeed,0xbed53e44,0x3ed5be44,0x3e8ebeed,
0x3ec6bf00,0xbea20000,0x3effbeb5,0x3d49beb5,0xbe71bdc8,0xbee23efb,0x3e15bed5,0xbef53e8e,0xbef53eed,0x3e153e44,0xbee23e44,0xbe713eed,0x3d493e8e,0x3effbed5,0xbea23efb,0x3ec6bdc8,
0xbeb53f00,0xbeb50000,0xbeb53f00,0xbeb50000,0x3eb50000,0xbeb53f00,0x3eb50000,0xbeb53f00,0x3eb5bf00,0x3eb50000,0x3eb5bf00,0x3eb50000,0xbeb50000,0x3eb5bf00,0xbeb50000,0x3eb5bf00,
0xbd49bf00,0xbeff0000,0xbec6beb5,0xbea23eb5,0x3e153efb,0x3ef5bdc8,0x3ee23e8e,0x3e71bed5,0xbe71beed,0xbee23e44,0xbef5be44,0xbe153eed,0x3ea23ed5,0x3ec6be8e,0x3eff3dc8,0x3d49befb,
0x3dc83f00,0x3efb0000,0x3efb0000,0xbdc8bf00,0xbe8ebeed,0xbed53e44,0xbed53e44,0x3e8e3eed,0x3ed53eb5,0x3e8ebeb5,0x3e8ebeb5,0xbed5beb5,0xbefbbe44,0xbdc83eed,0xbdc83eed,0x3efb3e44,
0xbe15bf00,0xbef50000,0xbe713eb5,0x3ee23eb5,0x3ec63ed5,0x3ea2be8e,0xbd49befb,0xbeffbdc8,0xbeffbe44,0xbd493eed,0x3ea23eed,0x3ec6be44,0x3ee2bdc8,0xbe71befb,0xbef5be8e,0xbe153ed5,
0x3e443f00,0x3eed0000,0xbe44bf00,0xbeed0000,0xbeedbeb5,0xbe443eb5,0x3eed3eb5,0x3e44beb5,0x3eed0000,0xbe44bf00,0xbeed0000,0x3e443f00,0xbe443eb5,0x3eed3eb5,0x3e44beb5,0xbeedbeb5,
0xbe71bf00,0xbee20000,0x3ef53eb5,0x3e15beb5,0x3eff3e8e,0x3d49bed5,0xbec63dc8,0x3ea23efb,0xbea23e44,0x3ec63eed,0xbd49beed,0xbeffbe44,0xbe15befb,0xbef5bdc8,0x3ee23ed5,0x3e71be8e,
0x3e8e3f00,0x3ed50000,0xbed50000,0x3e8e3f00,0xbefbbe44,0x3dc83eed,0xbdc8beed,0xbefbbe44,0x3dc8beb5,0xbefbbeb5,0x3efb3eb5,0x3dc8beb5,0x3ed53eed,0x3e8ebe44,0xbe8e3e44,0x3ed53eed,
0xbea2bf00,0xbec60000,0x3d49beb5,0xbeffbeb5,0x3ee23dc8,0xbe71befb,0x3ef53ed5,0x3e15be8e,0x3e153eed,0x3ef53e44,0xbe713e44,0x3ee23eed,0xbeffbe8e,0x3d493ed5,0xbec6befb,0xbea23dc8,
0x3f003f00,0xbf003f00,0x3f003f00,0xbf003f00,0x3f003f00,0xbf003f00,0x3f003f00,0xbf003f00,0x3f003f00,0xbf003f00,0x3f003f00,0xbf003f00,0x3f003f00,0xbf003f00,0x3f003f00,0xbf003f00,
0x3d490000,0x3eff3f00,0x3ec63eb5,0x3ea23eb5,0x3e153dc8,0x3ef53efb,0x3ee23ed5,0x3e713e8e,0x3e713e44,0x3ee23eed,0x3ef53eed,0x3e153e44,0x3ea23e8e,0x3ec63ed5,0x3eff3efb,0x3d493dc8,
0xbefbbf00,0x3dc80000,0x3dc80000,0x3efb3f00,0xbed5beed,0x3e8e3e44,0x3e8e3e44,0x3ed53eed,0xbe8ebeb5,0x3ed53eb5,0x3ed53eb5,0x3e8e3eb5,0xbdc8be44,0x3efb3eed,0x3efb3eed,0x3dc83e44,
0xbe150000,0xbef5bf00,0xbe71beb5,0x3ee23eb5,0xbec6be8e,0xbea2bed5,0x3d49bdc8,0x3eff3efb,0xbeffbeed,0xbd49be44,0x3ea23e44,0x3ec63eed,0xbee2befb,0x3e713dc8,0x3ef53ed5,0x3e153e8e,
0x3eed3f00,0xbe440000,0xbeedbf00,0x3e440000,0x3e443eb5,0xbeedbeb5,0xbe44beb5,0x3eed3eb5,0xbe440000,0xbeedbf00,0x3e440000,0x3eed3f00,0xbeedbeb5,0xbe44beb5,0x3eed3eb5,0x3e443eb5,
0x3e710000,0x3ee23f00,0xbef5beb5,0xbe15beb5,0x3eff3ed5,0x3d493e8e,0xbec6befb,0x3ea23dc8,0x3ea23eed,0xbec6be44,0x3d49be44,0x3eff3eed,0xbe153dc8,0xbef5befb,0x3ee23e8e,0x3e713ed5,
0xbed5bf00,0x3e8e0000,0xbe8e0000,0xbed5bf00,0x3dc8be44,0x3efb3eed,0xbefbbeed,0x3dc8be44,0x3efb3eb5,0x3dc83eb5,0xbdc8beb5,0x3efb3eb5,0x3e8e3eed,0xbed5be44,0x3ed53e44,0x3e8e3eed,
0xbea20000,0xbec6bf00,0x3d493eb5,0xbeffbeb5,0xbee2befb,0x3e71bdc8,0xbef5be8e,0xbe15bed5,0x3e15be44,0x3ef53eed,0xbe71beed,0x3ee23e44,0x3eff3ed5,0xbd493e8e,0x3ec63dc8,0x3ea23efb,
0x3f00,0xbf000000,0x3f00,0xbf000000,0xbf00,0x3f000000,0xbf00,0x3f000000,0x3f00,0xbf000000,0x3f00,0xbf000000,0xbf00,0x3f000000,0xbf00,0x3f000000,
0x3eff0000,0xbd493f00,0x3ea23eb5,0xbec63eb5,0xbef5bdc8,0x3e15befb,0xbe71bed5,0x3ee2be8e,0x3ee23e44,0xbe713eed,0x3e153eed,0xbef53e44,0xbec6be8e,0x3ea2bed5,0xbd49befb,0x3effbdc8,
0x3dc8bf00,0x3efb0000,0x3efb0000,0xbdc83f00,0xbe8e3eed,0xbed5be44,0xbed5be44,0x3e8ebeed,0x3ed5beb5,0x3e8e3eb5,0x3e8e3eb5,0xbed53eb5,0xbefb3e44,0xbdc8beed,0xbdc8beed,0x3efbbe44,
0xbef50000,0x3e15bf00,0x3ee2beb5,0x3e713eb5,0x3ea23e8e,0xbec63ed5,0xbeff3dc8,0x3d49befb,0xbd49beed,0x3effbe44,0x3ec63e44,0xbea23eed,0xbe713efb,0xbee2bdc8,0xbe15bed5,0x3ef5be8e,
0xbe443f00,0xbeed0000,0x3e44bf00,0x3eed0000,0x3eedbeb5,0x3e443eb5,0xbeed3eb5,0xbe44beb5,0xbeed0000,0x3e44bf00,0x3eed0000,0xbe443f00,0x3e443eb5,0xbeed3eb5,0xbe44beb5,0x3eedbeb5,
0x3ee20000,0xbe713f00,0xbe15beb5,0x3ef5beb5,0xbd49bed5,0x3effbe8e,0xbea23efb,0xbec6bdc8,0xbec63eed,0xbea2be44,0x3effbe44,0xbd493eed,0x3ef5bdc8,0xbe153efb,0xbe71be8e,0x3ee2bed5,
0x3e8ebf00,0x3ed50000,0xbed50000,0x3e8ebf00,0xbefb3e44,0x3dc8beed,0xbdc83eed,0xbefb3e44,0x3dc83eb5,0xbefb3eb5,0x3efbbeb5,0x3dc83eb5,0x3ed5beed,0x3e8e3e44,0xbe8ebe44,0x3ed5beed,
0xbec60000,0x3ea2bf00,0xbeff3eb5,0xbd49beb5,0xbe713efb,0xbee23dc8,0x3e153e8e,0xbef53ed5,0x3ef5be44,0xbe153eed,0x3ee2beed,0x3e713e44,0x3d49bed5,0x3effbe8e,0xbea2bdc8,0x3ec6befb,
0x3eb53f00,0xbeb50000,0x3eb53f00,0xbeb50000,0xbeb50000,0xbeb5bf00,0xbeb50000,0xbeb5bf00,0xbeb5bf00,0x3eb50000,0xbeb5bf00,0x3eb50000,0x3eb50000,0x3eb53f00,0x3eb50000,0x3eb53f00,
0xbd490000,0xbeff3f00,0xbec63eb5,0xbea23eb5,0xbe153dc8,0xbef53efb,0xbee23ed5,0xbe713e8e,0xbe713e44,0xbee23eed,0xbef53eed,0xbe153e44,0xbea23e8e,0xbec63ed5,0xbeff3efb,0xbd493dc8,
0x3efbbf00,0xbdc80000,0xbdc80000,0xbefb3f00,0x3ed5beed,0xbe8e3e44,0xbe8e3e44,0xbed53eed,0x3e8ebeb5,0xbed53eb5,0xbed53eb5,0xbe8e3eb5,0x3dc8be44,0xbefb3eed,0xbefb3eed,0xbdc83e44,
0x3e150000,0x3ef5bf00,0x3e71beb5,0xbee23eb5,0x3ec6be8e,0x3ea2bed5,0xbd49bdc8,0xbeff3efb,0x3effbeed,0x3d49be44,0xbea23e44,0xbec63eed,0x3ee2befb,0xbe713dc8,0xbef53ed5,0xbe153e8e,
0xbeed3f00,0x3e440000,0x3eedbf00,0xbe440000,0xbe443eb5,0x3eedbeb5,0x3e44beb5,0xbeed3eb5,0x3e440000,0x3eedbf00,0xbe440000,0xbeed3f00,0x3eedbeb5,0x3e44beb5,0xbeed3eb5,0xbe443eb5,
0xbe710000,0xbee23f00,0x3ef5beb5,0x3e15beb5,0xbeff3ed5,0xbd493e8e,0x3ec6befb,0xbea23dc8,0xbea23eed,0x3ec6be44,0xbd49be44,0xbeff3eed,0x3e153dc8,0x3ef5befb,0xbee23e8e,0xbe713ed5,
0x3ed5bf00,0xbe8e0000,0x3e8e0000,0x3ed5bf00,0xbdc8be44,0xbefb3eed,0x3efbbeed,0xbdc8be44,0xbefb3eb5,0xbdc83eb5,0x3dc8beb5,0xbefb3eb5,0xbe8e3eed,0x3ed5be44,0xbed53e44,0xbe8e3eed,
0x3ea20000,0x3ec6bf00,0xbd493eb5,0x3effbeb5,0x3ee2befb,0xbe71bdc8,0x3ef5be8e,0x3e15bed5,0xbe15be44,0xbef53eed,0x3e71beed,0xbee23e44,0xbeff3ed5,0x3d493e8e,0xbec63dc8,0xbea23efb,
0xbeb53f00,0xbeb50000,0xbeb53f00,0xbeb50000,0x3eb50000,0xbeb53f00,0x3eb50000,0xbeb53f00,0x3eb5bf00,0x3eb50000,0x3eb5bf00,0x3eb50000,0xbeb50000,0x3eb5bf00,0xbeb50000,0x3eb5bf00,
0xbeff0000,0x3d493f00,0xbea23eb5,0x3ec63eb5,0x3ef5bdc8,0xbe15befb,0x3e71bed5,0xbee2be8e,0xbee23e44,0x3e713eed,0xbe153eed,0x3ef53e44,0x3ec6be8e,0xbea2bed5,0x3d49befb,0xbeffbdc8,
0xbdc8bf00,0xbefb0000,0xbefb0000,0x3dc83f00,0x3e8e3eed,0x3ed5be44,0x3ed5be44,0xbe8ebeed,0xbed5beb5,0xbe8e3eb5,0xbe8e3eb5,0x3ed53eb5,0x3efb3e44,0x3dc8beed,0x3dc8beed,0xbefbbe44,
0x3ef50000,0xbe15bf00,0xbee2beb5,0xbe713eb5,0xbea23e8e,0x3ec63ed5,0x3eff3dc8,0xbd49befb,0x3d49beed,0xbeffbe44,0xbec63e44,0x3ea23eed,0x3e713efb,0x3ee2bdc8,0x3e15bed5,0xbef5be8e,
0x3e443f00,0x3eed0000,0xbe44bf00,0xbeed0000,0xbeedbeb5,0xbe443eb5,0x3eed3eb5,0x3e44beb5,0x3eed0000,0xbe44bf00,0xbeed0000,0x3e443f00,0xbe443eb5,0x3eed3eb5,0x3e44beb5,0xbeedbeb5,
0xbee20000,0x3e713f00,0x3e15beb5,0xbef5beb5,0x3d49bed5,0xbeffbe8e,0x3ea23efb,0x3ec6bdc8,0x3ec63eed,0x3ea2be44,0xbeffbe44,0x3d493eed,0xbef5bdc8,0x3e153efb,0x3e71be8e,0xbee2bed5,
0xbe8ebf00,0xbed50000,0x3ed50000,0xbe8ebf00,0x3efb3e44,0xbdc8beed,0x3dc83eed,0x3efb3e44,0xbdc83eb5,0x3efb3eb5,0xbefbbeb5,0xbdc83eb5,0xbed5beed,0xbe8e3e44,0x3e8ebe44,0xbed5beed,
0x3ec60000,0xbea2bf00,0x3eff3eb5,0x3d49beb5,0x3e713efb,0x3ee23dc8,0xbe153e8e,0x3ef53ed5,0xbef5be44,0x3e153eed,0xbee2beed,0xbe713e44,0xbd49bed5,0xbeffbe8e,0x3ea2bdc8,0xbec6befb,
0x3f800000,0x0,0x3f800000,0x0,0x3f800000,0x0,0x3f800000,0x0,0x3f800000,0x0,0x3f800000,0x0,0x3f800000,0x0,0x3f800000,0x0,
0x3f800000,0x0,0x3f7fec43,0xbcc90ab0,0x3f7fb10f,0xbd48fb30,0x3f7f4e6d,0xbd96a905,0x3f7ec46d,0xbdc8bd36,0x3f7e1324,0xbdfab273,0x3f7d3aac,0xbe164083,0x3f7c3b28,0xbe2f10a2,
0x3f800000,0x0,0x3f7ffec4,0xbbc90f88,0x3f7ffb11,0xbc490e90,0x3f7ff4e6,0xbc96c9b6,0x3f7fec43,0xbcc90ab0,0x3f7fe129,0xbcfb49ba,0x3f7fd397,0xbd16c32c,0x3f7fc38f,0xbd2fe007,
0x3f800000,0x0,0x3f7fe129,0xbcfb49ba,0x3f7f84ab,0xbd7b2b74,0x3f7eea9d,0xbdbc3ac3,0x3f7e1324,0xbdfab273,0x3f7cfe73,0xbe1c76de,0x3f7baccd,0xbe3b6ecf,0x3f7a1e84,0xbe5a3997,
0x3f800000,0x0,0x3f7ffb11,0xbc490e90,0x3f7fec43,0xbcc90ab0,0x3f7fd397,0xbd16c32c,0x3f7fb10f,0xbd48fb30,0x3f7f84ab,0xbd7b2b74,0x3f7f4e6d,0xbd96a905,0x3f7f0e58,0xbdafb680,
0x3f800000,0x0,0x3f7fd397,0xbd16c32c,0x3f7f4e6d,0xbd96a905,0x3f7e70b0,0xbde1bc2e,0x3f7d3aac,0xbe164083,0x3f7baccd,0xbe3b6ecf,0x3f79c79d,0xbe605c13,0x3f778bc5,0xbe827dc0,
0x3f800000,0x0,0x3f7ff4e6,0xbc96c9b6,0x3f7fd397,0xbd16c32c,0x3f7f9c18,0xbd621469,0x3f7f4e6d,0xbd96a905,0x3f7eea9d,0xbdbc3ac3,0x3f7e70b0,0xbde1bc2e,0x3f7de0b1,0xbe039502,
0x3f800000,0x0,0x3f7fc38f,0xbd2fe007,0x3f7f0e58,0xbdafb680,0x3f7de0b1,0xbe039502,0x3f7c3b28,0xbe2f10a2,0x3f7a1e84,0xbe5a3997,0x3f778bc5,0xbe827dc0,0x3f748422,0xbe97a117,
0x3f800000,0x0,0x3f7fb10f,0xbd48fb30,0x3f7ec46d,0xbdc8bd36,0x3f7d3aac,0xbe164083,0x3f7b14be,0xbe47c5c2,0x3f7853f8,0xbe78cfcc,0x3f74fa0b,0xbe94a031,0x3f710908,0xbeac7cd4,
0x3f800000,0x0,0x3f7f4e6d,0xbd96a905,0x3f7d3aac,0xbe164083,0x3f79c79d,0xbe605c13,0x3f74fa0b,0xbe94a031,0x3f6ed89e,0xbeb8442a,0x3f676bd8,0xbedae880,0x3f5ebe05,0xbefc5d27,
0x3f800000,0x0,0x3f7f9c18,0xbd621469,0x3f7e70b0,0xbde1bc2e,0x3f7c7eb0,0xbe28defc,0x3f79c79d,0xbe605c13,0x3f764d97,0xbe8b9507,0x3f721352,0xbea68f12,0x3f6d1c1d,0xbec1071e,
0x3f800000,0x0,0x3f7f2f9d,0xbda3308c,0x3f7cbfc9,0xbe22abb6,0x3f78b47b,0xbe72b651,0x3f731447,0xbea09ae5,0x3f6be858,0xbec6d529,0x3f633c5a,0xbeebcbbb,0x3f591e6a,0xbf07a136,
0x3f800000,0x0,0x3f7f84ab,0xbd7b2b74,0x3f7e1324,0xbdfab273,0x3f7baccd,0xbe3b6ecf,0x3f7853f8,0xbe78cfcc,0x3f740bdd,0xbe9aa086,0x3f6ed89e,0xbeb8442a,0x3f68bf3c,0xbed53641,
0x3f800000,0x0,0x3f7f0e58,0xbdafb680,0x3f7c3b28,0xbe2f10a2,0x3f778bc5,0xbe827dc0,0x3f710908,0xbeac7cd4,0x3f68bf3c,0xbed53641,0x3f5ebe05,0xbefc5d27,0x3f531849,0xbf10d3cd,
0x3f800000,0x0,0x3f7f6ac7,0xbd8a200a,0x3f7dabcc,0xbe09cf86,0x3f7ac516,0xbe4dee60,0x3f76ba07,0xbe888e93,0x3f718f57,0xbea986c4,0x3f6b4b0c,0xbec9b953,0x3f63f473,0xbee900b7,
0x3f800000,0x0,0x3f7eea9d,0xbdbc3ac3,0x3f7baccd,0xbe3b6ecf,0x3f764d97,0xbe8b9507,0x3f6ed89e,0xbeb8442a,0x3f655e0b,0xbee363fa,0x3f59f26a,0xbf064b82,0x3f4cae79,0xbf19c200,
0x3f800000,0x0,0x3f7ec46d,0xbdc8bd36,0x3f7b14be,0xbe47c5c2,0x3f74fa0b,0xbe94a031,0x3f6c835e,0xbec3ef15,0x3f61c598,0xbef15aea,0x3f54db31,0xbf0e39da,0x3f45e403,0xbf226799,
0x3f800000,0x0,0x3f7e1324,0xbdfab273,0x3f7853f8,0xbe78cfcc,0x3f6ed89e,0xbeb8442a,0x3f61c598,0xbef15aea,0x3f514d3d,0xbf13682a,0x3f3daef9,0xbf2beb4a,0x3f273656,0xbf41d870,
0x3f800000,0x0,0x3f7e9bc9,0xbdd53db9,0x3f7a7302,0xbe541501,0x3f73913f,0xbe9d9e78,0x3f6a09a7,0xbecf7bca,0x3f5df6be,0xbeff17b2,0x3f4f7a1f,0xbf15f6d9,0x3f3ebc1b,0xbf2ac082,
0x3f800000,0x0,0x3f7de0b1,0xbe039502,0x3f778bc5,0xbe827dc0,0x3f6d1c1d,0xbec1071e,0x3f5ebe05,0xbefc5d27,0x3f4cae79,0xbf19c200,0x3f373a23,0xbf32c8c9,0x3f1ebc12,0xbf48d8b3,
0x3f800000,0x0,0x3f7e70b0,0xbde1bc2e,0x3f79c79d,0xbe605c13,0x3f721352,0xbea68f12,0x3f676bd8,0xbedae880,0x3f59f26a,0xbf064b82,0x3f49d112,0xbf1d7fd1,0x3f373a23,0xbf32c8c9,
0x3f800000,0x0,0x3f7dabcc,0xbe09cf86,0x3f76ba07,0xbe888e93,0x3f6b4b0c,0xbec9b953,0x3f5b941a,0xbf039c3d,0x3f47de65,0xbf1ff6cb,0x3f3085bb,0xbf396842,0x3f15f6d9,0xbf4f7a1f,
0x3f800000,0x0,0x3f7e4323,0xbdee3876,0x3f791298,0xbe6c9a7f,0x3f708066,0xbeaf713a,0x3f64aa59,0xbee63375,0x3f55b993,0xbf0cead0,0x3f43e200,0xbf24d225,0x3f2f61a5,0xbf3a7ca4,
0x3f800000,0x0,0x3f7d7474,0xbe1008b7,0x3f75dec6,0xbe8e9a22,0x3f696591,0xbed25a09,0x3f584853,0xbf08f59b,0x3f42de29,0xbf26050a,0x3f299415,0xbf3fc767,0x3f0cead0,0xbf55b993,
0x3f800000,0x0,0x3f7d3aac,0xbe164083,0x3f74fa0b,0xbe94a031,0x3f676bd8,0xbedae880,0x3f54db31,0xbf0e39da,0x3f3daef9,0xbf2beb4a,0x3f226799,0xbf45e403,0x3f039c3d,0xbf5b941a,
0x3f800000,0x0,0x3f7c3b28,0xbe2f10a2,0x3f710908,0xbeac7cd4,0x3f5ebe05,0xbefc5d27,0x3f45e403,0xbf226799,0x3f273656,0xbf41d870,0x3f039c3d,0xbf5b941a,0x3eb8442a,0xbf6ed89e,
0x3f800000,0x0,0x3f7cfe73,0xbe1c76de,0x3f740bdd,0xbe9aa086,0x3f655e0b,0xbee363fa,0x3f514d3d,0xbf13682a,0x3f385216,0xbf31a81d,0x3f1b02c6,0xbf4bbbf8,0x3ef41f07,0xbf6106f2,
0x3f800000,0x0,0x3f7bf531,0xbe354098,0x3f6ff573,0xbeb263ef,0x3f5c61c7,0xbf0242b1,0x3f41d870,0xbf273656,0x3f212ff9,0xbf46e22a,0x3ef6e0cb,0xbf604621,0x3ea395c5,0xbf7294f8,
0x3f800000,0x0,0x3f7cbfc9,0xbe22abb6,0x3f731447,0xbea09ae5,0x3f633c5a,0xbeebcbbb,0x3f4d9f02,0xbf187fc0,0x3f32c8c9,0xbf373a23,0x3f13682a,0xbf514d3d,0x3ee0924f,0xbf660f88,
0x3f800000,0x0,0x3f7baccd,0xbe3b6ecf,0x3f6ed89e,0xbeb8442a,0x3f59f26a,0xbf064b82,0x3f3daef9,0xbf2beb4a,0x3f1b02c6,0xbf4bbbf8,0x3ee63375,0xbf64aa59,0x3e8e9a22,0xbf75dec6,
0x3f800000,0x0,0x3f7c7eb0,0xbe28defc,0x3f721352,0xbea68f12,0x3f6106f2,0xbef41f07,0x3f49d112,0xbf1d7fd1,0x3f2d1469,0xbf3ca003,0x3f0b9a6b,0xbf5695e5,0x3ecc9b8b,0xbf6aab7b,
0x3f800000,0x0,0x3f7b61fc,0xbe419b37,0x3f6db293,0xbebe1d4a,0x3f577026,0xbf0a48ad,0x3f396842,0xbf3085bb,0x3f14b039,0xbf5064af,0x3ed53641,0xbf68bf3c,0x3e72b651,0xbf78b47b,
0x3f800000,0x0,0x3f800000,0x0,0x3f800000,0x0,0x3f800000,0x0,0x3f800000,0x0,0x3f800000,0x0,0x3f800000,0x0,0x3f800000,0x0,
0x3f7b14be,0xbe47c5c2,0x3f79c79d,0xbe605c13,0x3f7853f8,0xbe78cfcc,0x3f76ba07,0xbe888e93,0x3f74fa0b,0xbe94a031,0x3f731447,0xbea09ae5,0x3f710908,0xbeac7cd4,0x3f6ed89e,0xbeb8442a,
0x3f7fb10f,0xbd48fb30,0x3f7f9c18,0xbd621469,0x3f7f84ab,0xbd7b2b74,0x3f7f6ac7,0xbd8a200a,0x3f7f4e6d,0xbd96a905,0x3f7f2f9d,0xbda3308c,0x3f7f0e58,0xbdafb680,0x3f7eea9d,0xbdbc3ac3,
0x3f7853f8,0xbe78cfcc,0x3f764d97,0xbe8b9507,0x3f740bdd,0xbe9aa086,0x3f718f57,0xbea986c4,0x3f6ed89e,0xbeb8442a,0x3f6be858,0xbec6d529,0x3f68bf3c,0xbed53641,0x3f655e0b,0xbee363fa,
0x3f7ec46d,0xbdc8bd36,0x3f7e70b0,0xbde1bc2e,0x3f7e1324,0xbdfab273,0x3f7dabcc,0xbe09cf86,0x3f7d3aac,0xbe164083,0x3f7cbfc9,0xbe22abb6,0x3f7c3b28,0xbe2f10a2,0x3f7baccd,0xbe3b6ecf,
0x3f74fa0b,0xbe94a031,0x3f721352,0xbea68f12,0x3f6ed89e,0xbeb8442a,0x3f6b4b0c,0xbec9b953,0x3f676bd8,0xbedae880,0x3f633c5a,0xbeebcbbb,0x3f5ebe05,0xbefc5d27,0x3f59f26a,0xbf064b82,
0x3f7d3aac,0xbe164083,0x3f7c7eb0,0xbe28defc,0x3f7baccd,0xbe3b6ecf,0x3f7ac516,0xbe4dee60,0x3f79c79d,0xbe605c13,0x3f78b47b,0xbe72b651,0x3f778bc5,0xbe827dc0,0x3f764d97,0xbe8b9507,
0x3f710908,0xbeac7cd4,0x3f6d1c1d,0xbec1071e,0x3f68bf3c,0xbed53641,0x3f63f473,0xbee900b7,0x3f5ebe05,0xbefc5d27,0x3f591e6a,0xbf07a136,0x3f531849,0xbf10d3cd,0x3f4cae79,0xbf19c200,
0x3f6c835e,0xbec3ef15,0x3f676bd8,0xbedae880,0x3f61c598,0xbef15aea,0x3f5b941a,0xbf039c3d,0x3f54db31,0xbf0e39da,0x3f4d9f02,0xbf187fc0,0x3f45e403,0xbf226799,0x3f3daef9,0xbf2beb4a,
0x3f54db31,0xbf0e39da,0x3f49d112,0xbf1d7fd1,0x3f3daef9,0xbf2beb4a,0x3f3085bb,0xbf396842,0x3f226799,0xbf45e403,0x3f13682a,0xbf514d3d,0x3f039c3d,0xbf5b941a,0x3ee63375,0xbf64aa59,
0x3f676bd8,0xbedae880,0x3f6106f2,0xbef41f07,0x3f59f26a,0xbf064b82,0x3f5233c6,0xbf121eb0,0x3f49d112,0xbf1d7fd1,0x3f40d0da,0xbf286605,0x3f373a23,0xbf32c8c9,0x3f2d1469,0xbf3ca003,
0x3f4d9f02,0xbf187fc0,0x3f40d0da,0xbf286605,0x3f32c8c9,0xbf373a23,0x3f239da9,0xbf44e3f5,0x3f13682a,0xbf514d3d,0x3f0242b1,0xbf5c61c7,0x3ee0924f,0xbf660f88,0x3ebb31a0,0xbf6e46be,
0x3f61c598,0xbef15aea,0x3f59f26a,0xbf064b82,0x3f514d3d,0xbf13682a,0x3f47de65,0xbf1ff6cb,0x3f3daef9,0xbf2beb4a,0x3f32c8c9,0xbf373a23,0x3f273656,0xbf41d870,0x3f1b02c6,0xbf4bbbf8,
0x3f45e403,0xbf226799,0x3f373a23,0xbf32c8c9,0x3f273656,0xbf41d870,0x3f15f6d9,0xbf4f7a1f,0x3f039c3d,0xbf5b941a,0x3ee0924f,0xbf660f88,0x3eb8442a,0xbf6ed89e,0x3e8e9a22,0xbf75dec6,
0x3f5b941a,0xbf039c3d,0x3f5233c6,0xbf121eb0,0x3f47de65,0xbf1ff6cb,0x3f3ca003,0xbf2d1469,0x3f3085bb,0xbf396842,0x3f239da9,0xbf44e3f5,0x3f15f6d9,0xbf4f7a1f,0x3f07a136,0xbf591e6a,
0x3f3daef9,0xbf2beb4a,0x3f2d1469,0xbf3ca003,0x3f1b02c6,0xbf4bbbf8,0x3f07a136,0xbf591e6a,0x3ee63375,0xbf64aa59,0x3ebb31a0,0xbf6e46be,0x3e8e9a22,0xbf75dec6,0x3e419b37,0xbf7b61fc,
0x3f3504f3,0xbf3504f3,0x3f226799,0xbf45e403,0x3f0e39da,0xbf54db31,0x3ef15aea,0xbf61c598,0x3ec3ef15,0xbf6c835e,0x3e94a031,0xbf74fa0b,0x3e47c5c2,0xbf7b14be,0x3dc8bd36,0xbf7ec46d,
0x3f0e39da,0xbf54db31,0x3ee63375,0xbf64aa59,0x3eac7cd4,0xbf710908,0x3e605c13,0xbf79c79d,0x3dc8bd36,0xbf7ec46d,0xbcc90ab0,0xbf7fec43,0xbe164083,0xbf7d3aac,0xbe888e93,0xbf76ba07,
0x3f2beb4a,0xbf3daef9,0x3f173c07,0xbf4e8d90,0x3f00e7e4,0xbf5d2d53,0x3ed25a09,0xbf696591,0x3ea09ae5,0xbf731447,0x3e5a3997,0xbf7a1e84,0x3de1bc2e,0xbf7e70b0,0x3bc90f88,0xbf7ffec4,
0x3f039c3d,0xbf5b941a,0x3ecc9b8b,0xbf6aab7b,0x3e8e9a22,0xbf75dec6,0x3e1c76de,0xbf7cfe73,0x3cc90ab0,0xbf7fec43,0xbdd53db9,0xbf7e9bc9,0xbe6c9a7f,0xbf791298,0xbeb554ec,0xbf6f6830,
0x3f226799,0xbf45e403,0x3f0b9a6b,0xbf5695e5,0x3ee63375,0xbf64aa59,0x3eb263ef,0xbf6ff573,0x3e78cfcc,0xbf7853f8,0x3e09cf86,0xbf7dabcc,0x3cc90ab0,0xbf7fec43,0xbdafb680,0xbf7f0e58,
0x3ef15aea,0xbf61c598,0x3eb263ef,0xbf6ff573,0x3e605c13,0xbf79c79d,0x3dafb680,0xbf7f0e58,0xbd48fb30,0xbf7fb10f,0xbe3b6ecf,0xbf7baccd,0xbea09ae5,0xbf731447,0xbee0924f,0xbf660f88,
0x3f187fc0,0xbf4d9f02,0x3eff17b2,0xbf5df6be,0x3ec9b953,0xbf6b4b0c,0x3e919ddd,0xbf756d97,0x3e2f10a2,0xbf7c3b28,0x3d621469,0xbf7f9c18,0xbd7b2b74,0xbf7f84ab,0xbe354098,0xbf7bf531,
0x3edae880,0xbf676bd8,0x3e97a117,0xbf748422,0x3e22abb6,0xbf7cbfc9,0x3c96c9b6,0xbf7ff4e6,0xbdfab273,0xbf7e1324,0xbe8586ce,0xbf772417,0xbec9b953,0xbf6b4b0c,0xbf04f484,0xbf5ac450,
0x3ec3ef15,0xbf6c835e,0x3e78cfcc,0xbf7853f8,0x3dc8bd36,0xbf7ec46d,0xbd48fb30,0xbf7fb10f,0xbe47c5c2,0xbf7b14be,0xbeac7cd4,0xbf710908,0xbef15aea,0xbf61c598,0xbf187fc0,0xbf4d9f02,
0x3e47c5c2,0xbf7b14be,0x3cc90ab0,0xbf7fec43,0xbe164083,0xbf7d3aac,0xbea09ae5,0xbf731447,0xbef15aea,0xbf61c598,0xbf1d7fd1,0xbf49d112,0xbf3daef9,0xbf2beb4a,0xbf584853,0xbf08f59b,
0x3eac7cd4,0xbf710908,0x3e419b37,0xbf7b61fc,0x3d16c32c,0xbf7fd397,0xbdee3876,0xbf7e4323,0xbe888e93,0xbf76ba07,0xbed25a09,0xbf696591,0xbf0b9a6b,0xbf5695e5,0xbf2ac082,0xbf3ebc1b,
0x3e164083,0xbf7d3aac,0xbcfb49ba,0xbf7fe129,0xbe541501,0xbf7a7302,0xbec1071e,0xbf6d1c1d,0xbf08f59b,0xbf584853,0xbf2d1469,0xbf3ca003,0xbf4bbbf8,0xbf1b02c6,0xbf63f473,0xbee900b7,
0x3e94a031,0xbf74fa0b,0x3e09cf86,0xbf7dabcc,0xbcc90ab0,0xbf7fec43,0xbe3b6ecf,0xbf7baccd,0xbeac7cd4,0xbf710908,0xbef6e0cb,0xbf604621,0xbf1d7fd1,0xbf49d112,0xbf3b8f3b,0xbf2e3bde,
0x3dc8bd36,0xbf7ec46d,0xbdafb680,0xbf7f0e58,0xbe888e93,0xbf76ba07,0xbee0924f,0xbf660f88,0xbf187fc0,0xbf4d9f02,0xbf3b8f3b,0xbf2e3bde,0xbf584853,0xbf08f59b,0xbf6db293,0xbebe1d4a,
0x3e78cfcc,0xbf7853f8,0x3da3308c,0xbf7f2f9d,0xbdafb680,0xbf7f0e58,0xbe7ee6e1,0xbf77f110,0xbecf7bca,0xbf6a09a7,0xbf0cead0,0xbf55b993,0xbf2e3bde,0xbf3b8f3b,0xbf4ac77f,0xbf1c420c,
0x3d48fb30,0xbf7fb10f,0xbe1008b7,0xbf7d7474,0xbea68f12,0xbf721352,0xbeff17b2,0xbf5df6be,0xbf273656,0xbf41d870,0xbf48d8b3,0xbf1ebc12,0xbf633c5a,0xbeebcbbb,0xbf756d97,0xbe919ddd,
0x3f800000,0x0,0x3f800000,0x0,0x3f800000,0x0,0x3f800000,0x0,0x3f800000,0x0,0x3f800000,0x0,0x3f800000,0x0,0x3f800000,0x0,
0x3f6c835e,0xbec3ef15,0x3f6a09a7,0xbecf7bca,0x3f676bd8,0xbedae880,0x3f64aa59,0xbee63375,0x3f61c598,0xbef15aea,0x3f5ebe05,0xbefc5d27,0x3f5b941a,0xbf039c3d,0x3f584853,0xbf08f59b,
0x3f7ec46d,0xbdc8bd36,0x3f7e9bc9,0xbdd53db9,0x3f7e70b0,0xbde1bc2e,0x3f7e4323,0xbdee3876,0x3f7e1324,0xbdfab273,0x3f7de0b1,0xbe039502,0x3f7dabcc,0xbe09cf86,0x3f7d7474,0xbe1008b7,
0x3f61c598,0xbef15aea,0x3f5df6be,0xbeff17b2,0x3f59f26a,0xbf064b82,0x3f55b993,0xbf0cead0,0x3f514d3d,0xbf13682a,0x3f4cae79,0xbf19c200,0x3f47de65,0xbf1ff6cb,0x3f42de29,0xbf26050a,
0x3f7b14be,0xbe47c5c2,0x3f7a7302,0xbe541501,0x3f79c79d,0xbe605c13,0x3f791298,0xbe6c9a7f,0x3f7853f8,0xbe78cfcc,0x3f778bc5,0xbe827dc0,0x3f76ba07,0xbe888e93,0x3f75dec6,0xbe8e9a22,
0x3f54db31,0xbf0e39da,0x3f4f7a1f,0xbf15f6d9,0x3f49d112,0xbf1d7fd1,0x3f43e200,0xbf24d225,0x3f3daef9,0xbf2beb4a,0x3f373a23,0xbf32c8c9,0x3f3085bb,0xbf396842,0x3f299415,0xbf3fc767,
0x3f74fa0b,0xbe94a031,0x3f73913f,0xbe9d9e78,0x3f721352,0xbea68f12,0x3f708066,0xbeaf713a,0x3f6ed89e,0xbeb8442a,0x3f6d1c1d,0xbec1071e,0x3f6b4b0c,0xbec9b953,0x3f696591,0xbed25a09,
0x3f45e403,0xbf226799,0x3f3ebc1b,0xbf2ac082,0x3f373a23,0xbf32c8c9,0x3f2f61a5,0xbf3a7ca4,0x3f273656,0xbf41d870,0x3f1ebc12,0xbf48d8b3,0x3f15f6d9,0xbf4f7a1f,0x3f0cead0,0xbf55b993,
0x3f3504f3,0xbf3504f3,0x3f2beb4a,0xbf3daef9,0x3f226799,0xbf45e403,0x3f187fc0,0xbf4d9f02,0x3f0e39da,0xbf54db31,0x3f039c3d,0xbf5b941a,0x3ef15aea,0xbf61c598,0x3edae880,0xbf676bd8,
0x3ec3ef15,0xbf6c835e,0x3ea09ae5,0xbf731447,0x3e78cfcc,0xbf7853f8,0x3e2f10a2,0xbf7c3b28,0x3dc8bd36,0xbf7ec46d,0x3cc90ab0,0xbf7fec43,0xbd48fb30,0xbf7fb10f,0xbdfab273,0xbf7e1324,
0x3f226799,0xbf45e403,0x3f173c07,0xbf4e8d90,0x3f0b9a6b,0xbf5695e5,0x3eff17b2,0xbf5df6be,0x3ee63375,0xbf64aa59,0x3ecc9b8b,0xbf6aab7b,0x3eb263ef,0xbf6ff573,0x3e97a117,0xbf748422,
0x3e94a031,0xbf74fa0b,0x3e5a3997,0xbf7a1e84,0x3e09cf86,0xbf7dabcc,0x3d621469,0xbf7f9c18,0xbcc90ab0,0xbf7fec43,0xbdd53db9,0xbf7e9bc9,0xbe3b6ecf,0xbf7baccd,0xbe8586ce,0xbf772417,
0x3f0e39da,0xbf54db31,0x3f00e7e4,0xbf5d2d53,0x3ee63375,0xbf64aa59,0x3ec9b953,0xbf6b4b0c,0x3eac7cd4,0xbf710908,0x3e8e9a22,0xbf75dec6,0x3e605c13,0xbf79c79d,0x3e22abb6,0xbf7cbfc9,
0x3e47c5c2,0xbf7b14be,0x3de1bc2e,0xbf7e70b0,0x3cc90ab0,0xbf7fec43,0xbd7b2b74,0xbf7f84ab,0xbe164083,0xbf7d3aac,0xbe6c9a7f,0xbf791298,0xbea09ae5,0xbf731447,0xbec9b953,0xbf6b4b0c,
0x3ef15aea,0xbf61c598,0x3ed25a09,0xbf696591,0x3eb263ef,0xbf6ff573,0x3e919ddd,0xbf756d97,0x3e605c13,0xbf79c79d,0x3e1c76de,0xbf7cfe73,0x3dafb680,0xbf7f0e58,0x3c96c9b6,0xbf7ff4e6,
0x3dc8bd36,0xbf7ec46d,0x3bc90f88,0xbf7ffec4,0xbdafb680,0xbf7f0e58,0xbe354098,0xbf7bf531,0xbe888e93,0xbf76ba07,0xbeb554ec,0xbf6f6830,0xbee0924f,0xbf660f88,0xbf04f484,0xbf5ac450,
0x0,0xbf800000,0xbdc8bd36,0xbf7ec46d,0xbe47c5c2,0xbf7b14be,0xbe94a031,0xbf74fa0b,0xbec3ef15,0xbf6c835e,0xbef15aea,0xbf61c598,0xbf0e39da,0xbf54db31,0xbf226799,0xbf45e403,
0xbec3ef15,0xbf6c835e,0xbefc5d27,0xbf5ebe05,0xbf187fc0,0xbf4d9f02,0xbf3085bb,0xbf396842,0xbf45e403,0xbf226799,0xbf584853,0xbf08f59b,0xbf676bd8,0xbedae880,0xbf731447,0xbea09ae5,
0xbdc8bd36,0xbf7ec46d,0xbe4dee60,0xbf7ac516,0xbe9aa086,0xbf740bdd,0xbecc9b8b,0xbf6aab7b,0xbefc5d27,0xbf5ebe05,0xbf14b039,0xbf5064af,0xbf299415,0xbf3fc767,0xbf3ca003,0xbf2d1469,
0xbef15aea,0xbf61c598,0xbf14b039,0xbf5064af,0xbf2e3bde,0xbf3b8f3b,0xbf44e3f5,0xbf239da9,0xbf584853,0xbf08f59b,0xbf6816a8,0xbed8106b,0xbf740bdd,0xbe9aa086,0xbf7bf531,0xbe354098,
0xbe47c5c2,0xbf7b14be,0xbe9aa086,0xbf740bdd,0xbecf7bca,0xbf6a09a7,0xbf00e7e4,0xbf5d2d53,0xbf187fc0,0xbf4d9f02,0xbf2e3bde,0xbf3b8f3b,0xbf41d870,0xbf273656,0xbf531849,0xbf10d3cd,
0xbf0e39da,0xbf54db31,0xbf299415,0xbf3fc767,0xbf41d870,0xbf273656,0xbf5695e5,0xbf0b9a6b,0xbf676bd8,0xbedae880,0xbf740bdd,0xbe9aa086,0xbf7c3b28,0xbe2f10a2,0xbf7fd397,0xbd16c32c,
0xbe94a031,0xbf74fa0b,0xbecc9b8b,0xbf6aab7b,0xbf00e7e4,0xbf5d2d53,0xbf19c200,0xbf4cae79,0xbf3085bb,0xbf396842,0xbf44e3f5,0xbf239da9,0xbf5695e5,0xbf0b9a6b,0xbf655e0b,0xbee363fa,
0xbf226799,0xbf45e403,0xbf3ca003,0xbf2d1469,0xbf531849,0xbf10d3cd,0xbf655e0b,0xbee363fa,0xbf731447,0xbea09ae5,0xbf7bf531,0xbe354098,0xbf7fd397,0xbd16c32c,0xbf7e9bc9,0x3dd53db9,
0xbf3504f3,0xbf3504f3,0xbf4d9f02,0xbf187fc0,0xbf61c598,0xbef15aea,0xbf710908,0xbeac7cd4,0xbf7b14be,0xbe47c5c2,0xbf7fb10f,0xbd48fb30,0xbf7ec46d,0x3dc8bd36,0xbf7853f8,0x3e78cfcc,
0xbf6c835e,0xbec3ef15,0xbf79c79d,0xbe605c13,0xbf7fb10f,0xbd48fb30,0xbf7e1324,0x3dfab273,0xbf74fa0b,0x3e94a031,0xbf64aa59,0x3ee63375,0xbf4d9f02,0x3f187fc0,0xbf3085bb,0x3f396842,
0xbf45e403,0xbf226799,0xbf5c61c7,0xbf0242b1,0xbf6db293,0xbebe1d4a,0xbf796e4e,0xbe667c66,0xbf7f4e6d,0xbd96a905,0xbf7f2f9d,0x3da3308c,0xbf791298,0x3e6c9a7f,0xbf6d1c1d,0x3ec1071e,
0xbf74fa0b,0xbe94a031,0xbf7e4323,0xbdee3876,0xbf7f84ab,0x3d7b2b74,0xbf78b47b,0x3e72b651,0xbf6a09a7,0x3ecf7bca,0xbf53fac3,0x3f0f8784,0xbf373a23,0x3f32c8c9,0xbf14b039,0x3f5064af,
0xbf54db31,0xbf0e39da,0xbf68bf3c,0xbed53641,0xbf76ba07,0xbe888e93,0xbf7e70b0,0xbde1bc2e,0xbf7fb10f,0x3d48fb30,0xbf7a7302,0x3e541501,0xbf6ed89e,0x3eb8442a,0xbf5d2d53,0x3f00e7e4,
0xbf7b14be,0xbe47c5c2,0xbf7ffb11,0xbc490e90,0xbf7c3b28,0x3e2f10a2,0xbf6ff573,0x3eb263ef,0xbf5b941a,0x3f039c3d,0xbf3fc767,0x3f299415,0xbf1d7fd1,0x3f49d112,0xbeebcbbb,0x3f633c5a,
0xbf61c598,0xbef15aea,0xbf7294f8,0xbea395c5,0xbf7cbfc9,0xbe22abb6,0xbf7ffec4,0x3bc90f88,0xbf7c3b28,0x3e2f10a2,0xbf718f57,0x3ea986c4,0xbf604621,0x3ef6e0cb,0xbf48d8b3,0x3f1ebc12,
0xbf7ec46d,0xbdc8bd36,0xbf7eea9d,0x3dbc3ac3,0xbf75dec6,0x3e8e9a22,0xbf63f473,0x3ee900b7,0xbf49d112,0x3f1d7fd1,0xbf286605,0x3f40d0da,0xbf00e7e4,0x3f5d2d53,0xbea986c4,0x3f718f57,
0x3f800000,0x0,0x3f800000,0x0,0x3f800000,0x0,0x3f800000,0x0,0x3f800000,0x0,0x3f800000,0x0,0x3f800000,0x0,0x3f800000,0x0,
0x3f54db31,0xbf0e39da,0x3f514d3d,0xbf13682a,0x3f4d9f02,0xbf187fc0,0x3f49d112,0xbf1d7fd1,0x3f45e403,0xbf226799,0x3f41d870,0xbf273656,0x3f3daef9,0xbf2beb4a,0x3f396842,0xbf3085bb,
0x3f7d3aac,0xbe164083,0x3f7cfe73,0xbe1c76de,0x3f7cbfc9,0xbe22abb6,0x3f7c7eb0,0xbe28defc,0x3f7c3b28,0xbe2f10a2,0x3f7bf531,0xbe354098,0x3f7baccd,0xbe3b6ecf,0x3f7b61fc,0xbe419b37,
0x3f3daef9,0xbf2beb4a,0x3f385216,0xbf31a81d,0x3f32c8c9,0xbf373a23,0x3f2d1469,0xbf3ca003,0x3f273656,0xbf41d870,0x3f212ff9,0xbf46e22a,0x3f1b02c6,0xbf4bbbf8,0x3f14b039,0xbf5064af,
0x3f74fa0b,0xbe94a031,0x3f740bdd,0xbe9aa086,0x3f731447,0xbea09ae5,0x3f721352,0xbea68f12,0x3f710908,0xbeac7cd4,0x3f6ff573,0xbeb263ef,0x3f6ed89e,0xbeb8442a,0x3f6db293,0xbebe1d4a,
0x3f226799,0xbf45e403,0x3f1b02c6,0xbf4bbbf8,0x3f13682a,0xbf514d3d,0x3f0b9a6b,0xbf5695e5,0x3f039c3d,0xbf5b941a,0x3ef6e0cb,0xbf604621,0x3ee63375,0xbf64aa59,0x3ed53641,0xbf68bf3c,
0x3f676bd8,0xbedae880,0x3f655e0b,0xbee363fa,0x3f633c5a,0xbeebcbbb,0x3f6106f2,0xbef41f07,0x3f5ebe05,0xbefc5d27,0x3f5c61c7,0xbf0242b1,0x3f59f26a,0xbf064b82,0x3f577026,0xbf0a48ad,
0x3f039c3d,0xbf5b941a,0x3ef41f07,0xbf6106f2,0x3ee0924f,0xbf660f88,0x3ecc9b8b,0xbf6aab7b,0x3eb8442a,0xbf6ed89e,0x3ea395c5,0xbf7294f8,0x3e8e9a22,0xbf75dec6,0x3e72b651,0xbf78b47b,
0x3ec3ef15,0xbf6c835e,0x3eac7cd4,0xbf710908,0x3e94a031,0xbf74fa0b,0x3e78cfcc,0xbf7853f8,0x3e47c5c2,0xbf7b14be,0x3e164083,0xbf7d3aac,0x3dc8bd36,0xbf7ec46d,0x3d48fb30,0xbf7fb10f,
0xbe47c5c2,0xbf7b14be,0xbe888e93,0xbf76ba07,0xbeac7cd4,0xbf710908,0xbecf7bca,0xbf6a09a7,0xbef15aea,0xbf61c598,0xbf08f59b,0xbf584853,0xbf187fc0,0xbf4d9f02,0xbf273656,0xbf41d870,
0x3e78cfcc,0xbf7853f8,0x3e419b37,0xbf7b61fc,0x3e09cf86,0xbf7dabcc,0x3da3308c,0xbf7f2f9d,0x3cc90ab0,0xbf7fec43,0xbcfb49ba,0xbf7fe129,0xbdafb680,0xbf7f0e58,0xbe1008b7,0xbf7d7474,
0xbeac7cd4,0xbf710908,0xbed25a09,0xbf696591,0xbef6e0cb,0xbf604621,0xbf0cead0,0xbf55b993,0xbf1d7fd1,0xbf49d112,0xbf2d1469,0xbf3ca003,0xbf3b8f3b,0xbf2e3bde,0xbf48d8b3,0xbf1ebc12,
0x3dc8bd36,0xbf7ec46d,0x3d16c32c,0xbf7fd397,0xbcc90ab0,0xbf7fec43,0xbdafb680,0xbf7f0e58,0xbe164083,0xbf7d3aac,0xbe541501,0xbf7a7302,0xbe888e93,0xbf76ba07,0xbea68f12,0xbf721352,
0xbef15aea,0xbf61c598,0xbf0b9a6b,0xbf5695e5,0xbf1d7fd1,0xbf49d112,0xbf2e3bde,0xbf3b8f3b,0xbf3daef9,0xbf2beb4a,0xbf4bbbf8,0xbf1b02c6,0xbf584853,0xbf08f59b,0xbf633c5a,0xbeebcbbb,
0xbd48fb30,0xbf7fb10f,0xbdee3876,0xbf7e4323,0xbe3b6ecf,0xbf7baccd,0xbe7ee6e1,0xbf77f110,0xbea09ae5,0xbf731447,0xbec1071e,0xbf6d1c1d,0xbee0924f,0xbf660f88,0xbeff17b2,0xbf5df6be,
0xbf187fc0,0xbf4d9f02,0xbf2ac082,0xbf3ebc1b,0xbf3b8f3b,0xbf2e3bde,0xbf4ac77f,0xbf1c420c,0xbf584853,0xbf08f59b,0xbf63f473,0xbee900b7,0xbf6db293,0xbebe1d4a,0xbf756d97,0xbe919ddd,
0xbf3504f3,0xbf3504f3,0xbf45e403,0xbf226799,0xbf54db31,0xbf0e39da,0xbf61c598,0xbef15aea,0xbf6c835e,0xbec3ef15,0xbf74fa0b,0xbe94a031,0xbf7b14be,0xbe47c5c2,0xbf7ec46d,0xbdc8bd36,
0xbf7b14be,0xbe47c5c2,0xbf7f4e6d,0xbd96a905,0xbf7fb10f,0x3d48fb30,0xbf7c3b28,0x3e2f10a2,0xbf74fa0b,0x3e94a031,0xbf6a09a7,0x3ecf7bca,0xbf5b941a,0x3f039c3d,0xbf49d112,0x3f1d7fd1,
0xbf4d9f02,0xbf187fc0,0xbf5c61c7,0xbf0242b1,0xbf68bf3c,0xbed53641,0xbf7294f8,0xbea395c5,0xbf79c79d,0xbe605c13,0xbf7e4323,0xbdee3876,0xbf7ffb11,0xbc490e90,0xbf7eea9d,0x3dbc3ac3,
0xbf7fb10f,0xbd48fb30,0xbf7f2f9d,0x3da3308c,0xbf7a7302,0x3e541501,0xbf718f57,0x3ea986c4,0xbf64aa59,0x3ee63375,0xbf53fac3,0x3f0f8784,0xbf3fc767,0x3f299415,0xbf286605,0x3f40d0da,
0xbf61c598,0xbef15aea,0xbf6db293,0xbebe1d4a,0xbf76ba07,0xbe888e93,0xbf7cbfc9,0xbe22abb6,0xbf7fb10f,0xbd48fb30,0xbf7f84ab,0x3d7b2b74,0xbf7c3b28,0x3e2f10a2,0xbf75dec6,0x3e8e9a22,
0xbf7ec46d,0x3dc8bd36,0xbf791298,0x3e6c9a7f,0xbf6ed89e,0x3eb8442a,0xbf604621,0x3ef6e0cb,0xbf4d9f02,0x3f187fc0,0xbf373a23,0x3f32c8c9,0xbf1d7fd1,0x3f49d112,0xbf00e7e4,0x3f5d2d53,
0xbf710908,0xbeac7cd4,0xbf796e4e,0xbe667c66,0xbf7e70b0,0xbde1bc2e,0xbf7ffec4,0x3bc90f88,0xbf7e1324,0x3dfab273,0xbf78b47b,0x3e72b651,0xbf6ff573,0x3eb263ef,0xbf63f473,0x3ee900b7,
0xbf7853f8,0x3e78cfcc,0xbf6d1c1d,0x3ec1071e,0xbf5d2d53,0x3f00e7e4,0xbf48d8b3,0x3f1ebc12,0xbf3085bb,0x3f396842,0xbf14b039,0x3f5064af,0xbeebcbbb,0x3f633c5a,0xbea986c4,0x3f718f57,
0xbf6c835e,0x3ec3ef15,0xbf5b941a,0x3f039c3d,0xbf45e403,0x3f226799,0xbf2beb4a,0x3f3daef9,0xbf0e39da,0x3f54db31,0xbedae880,0x3f676bd8,0xbe94a031,0x3f74fa0b,0xbe164083,0x3f7d3aac,
0xbf0e39da,0x3f54db31,0xbecf7bca,0x3f6a09a7,0xbe78cfcc,0x3f7853f8,0xbd96a905,0x3f7f4e6d,0x3dc8bd36,0x3f7ec46d,0x3e888e93,0x3f76ba07,0x3edae880,0x3f676bd8,0x3f13682a,0x3f514d3d,
0xbf5b941a,0x3f039c3d,0xbf44e3f5,0x3f239da9,0xbf299415,0x3f3fc767,0xbf0a48ad,0x3f577026,0xbecf7bca,0x3f6a09a7,0xbe8586ce,0x3f772417,0xbde1bc2e,0x3f7e70b0,0x3d2fe007,0x3f7fc38f,
0xbedae880,0x3f676bd8,0xbe8586ce,0x3f772417,0xbdafb680,0x3f7f0e58,0x3dbc3ac3,0x3f7eea9d,0x3e888e93,0x3f76ba07,0x3eddbe79,0x3f66becc,0x3f15f6d9,0x3f4f7a1f,0x3f385216,0x3f31a81d,
0xbf45e403,0x3f226799,0xbf299415,0x3f3fc767,0xbf08f59b,0x3f584853,0xbec9b953,0x3f6b4b0c,0xbe78cfcc,0x3f7853f8,0xbdafb680,0x3f7f0e58,0x3d96a905,0x3f7f4e6d,0x3e6c9a7f,0x3f791298,
0xbe94a031,0x3f74fa0b,0xbde1bc2e,0x3f7e70b0,0x3d96a905,0x3f7f4e6d,0x3e827dc0,0x3f778bc5,0x3edae880,0x3f676bd8,0x3f15f6d9,0x3f4f7a1f,0x3f396842,0x3f3085bb,0x3f5695e5,0x3f0b9a6b,
0xbf2beb4a,0x3f3daef9,0xbf0a48ad,0x3f577026,0xbec9b953,0x3f6b4b0c,0xbe72b651,0x3f78b47b,0xbd96a905,0x3f7f4e6d,0x3dbc3ac3,0x3f7eea9d,0x3e827dc0,0x3f778bc5,0x3ed25a09,0x3f696591,
0xbe164083,0x3f7d3aac,0x3d2fe007,0x3f7fc38f,0x3e6c9a7f,0x3f791298,0x3ed25a09,0x3f696591,0x3f13682a,0x3f514d3d,0x3f385216,0x3f31a81d,0x3f5695e5,0x3f0b9a6b,0x3f6d1c1d,0x3ec1071e,
0x3e00,0x3e00,0x3e00,0x3e00,0x3e00,0x3e00,0x3e00,0x3e00,0x3e00,0x3e00,0x3e00,0x3e00,0x3e00,0x3e00,0x3e00,0x3e00,
0xbd443ded,0xbcc83dfb,0xbc493dff,0xbd153df5,0xbdb53db5,0xbdd53d8e,0xbdc63da2,0xbde23d71,0xbe000000,0xbdfbbcc8,0xbdffbc49,0xbdf5bd15,0xbdb5bdb5,0xbd8ebdd5,0xbda2bdc6,0xbd71bde2,
0xbdb53db5,0xbd443ded,0xbcc83dfb,0xbd8e3dd5,0xbe000000,0xbdedbd44,0xbdfbbcc8,0xbdd5bd8e,0xbe00,0x3d44bded,0x3cc8bdfb,0x3d8ebdd5,0x3e000000,0x3ded3d44,0x3dfb3cc8,0x3dd53d8e,
0xbded3d44,0xbd8e3dd5,0xbd153df5,0xbdc63da2,0xbdb5bdb5,0xbcc8bdfb,0xbd71bde2,0x3c49bdff,0x3e000000,0x3dd53d8e,0x3df53d15,0x3da23dc6,0xbdb53db5,0xbdfb3cc8,0xbde23d71,0xbdffbc49,
0xbe000000,0xbdb53db5,0xbd443ded,0xbded3d44,0xbe00,0x3db5bdb5,0x3d44bded,0x3dedbd44,0x3e00,0xbdb53db5,0xbd443ded,0xbded3d44,0xbe00,0x3db5bdb5,0x3d44bded,0x3dedbd44,
0xbdedbd44,0xbdd53d8e,0xbd713de2,0xbdff3c49,0x3db5bdb5,0x3dfb3cc8,0x3df5bd15,0x3dc63da2,0xbe000000,0xbd8ebdd5,0xbde2bd71,0xbc49bdff,0x3db53db5,0xbcc83dfb,0x3d153df5,0xbda23dc6,
0xbdb5bdb5,0xbded3d44,0xbd8e3dd5,0xbdfbbcc8,0x3e000000,0x3d443ded,0x3dd53d8e,0xbcc83dfb,0xbe00,0x3dedbd44,0x3d8ebdd5,0x3dfb3cc8,0xbe000000,0xbd44bded,0xbdd5bd8e,0x3cc8bdfb,
0xbd44bded,0xbdfb3cc8,0xbda23dc6,0xbde2bd71,0x3db53db5,0xbd8e3dd5,0x3c493dff,0xbdf53d15,0x3e000000,0x3cc83dfb,0x3dc63da2,0xbd713de2,0x3db5bdb5,0x3dd53d8e,0x3dffbc49,0x3d153df5,
0xbe00,0xbe000000,0xbdb53db5,0xbdb5bdb5,0x3e00,0xbe000000,0xbdb53db5,0xbdb5bdb5,0x3e00,0xbe000000,0xbdb53db5,0xbdb5bdb5,0x3e00,0xbe000000,0xbdb53db5,0xbdb5bdb5,
0x3d44bded,0xbdfbbcc8,0xbdc63da2,0xbd71bde2,0xbdb53db5,0xbd8ebdd5,0xbdffbc49,0x3d15bdf5,0xbe000000,0x3cc8bdfb,0xbda2bdc6,0x3de2bd71,0xbdb5bdb5,0x3dd5bd8e,0x3c49bdff,0x3df53d15,
0x3db5bdb5,0xbdedbd44,0xbdd53d8e,0xbcc8bdfb,0xbe000000,0x3d44bded,0xbd8ebdd5,0x3dfbbcc8,0xbe00,0x3ded3d44,0x3dd5bd8e,0x3cc83dfb,0x3e000000,0xbd443ded,0x3d8e3dd5,0xbdfb3cc8,
0x3dedbd44,0xbdd5bd8e,0xbde23d71,0x3c49bdff,0xbdb5bdb5,0x3dfbbcc8,0x3d15bdf5,0x3da23dc6,0x3e000000,0xbd8e3dd5,0x3d713de2,0xbdffbc49,0xbdb53db5,0xbcc8bdfb,0xbdf5bd15,0x3dc6bda2,
0x3e000000,0xbdb5bdb5,0xbded3d44,0x3d44bded,0xbe00,0x3db53db5,0x3dedbd44,0xbd443ded,0x3e00,0xbdb5bdb5,0xbded3d44,0x3d44bded,0xbe00,0x3db53db5,0x3dedbd44,0xbd443ded,
0x3ded3d44,0xbd8ebdd5,0xbdf53d15,0x3da2bdc6,0x3db5bdb5,0xbcc83dfb,0x3de23d71,0xbdff3c49,0xbe000000,0x3dd5bd8e,0xbd15bdf5,0x3dc63da2,0x3db53db5,0xbdfbbcc8,0xbd713de2,0xbc49bdff,
0x3db53db5,0xbd44bded,0xbdfb3cc8,0x3dd5bd8e,0x3e000000,0xbded3d44,0x3cc83dfb,0xbd8ebdd5,0xbe00,0x3d443ded,0x3dfbbcc8,0xbdd53d8e,0xbe000000,0x3dedbd44,0xbcc8bdfb,0x3d8e3dd5,
0x3d443ded,0xbcc8bdfb,0xbdff3c49,0x3df5bd15,0x3db53db5,0xbdd5bd8e,0xbda23dc6,0x3d71bde2,0x3e000000,0xbdfb3cc8,0x3c493dff,0xbd15bdf5,0x3db5bdb5,0xbd8e3dd5,0x3dc63da2,0xbde2bd71,
0x3e00,0xbe00,0xbe000000,0x3e000000,0x3e00,0xbe00,0xbe000000,0x3e000000,0x3e00,0xbe00,0xbe000000,0x3e000000,0x3e00,0xbe00,0xbe000000,0x3e000000,
0xbd443ded,0x3cc8bdfb,0xbdffbc49,0x3df53d15,0xbdb53db5,0x3dd5bd8e,0xbda2bdc6,0x3d713de2,0xbe000000,0x3dfb3cc8,0x3c49bdff,0xbd153df5,0xbdb5bdb5,0x3d8e3dd5,0x3dc6bda2,0xbde23d71,
0xbdb53db5,0x3d44bded,0xbdfbbcc8,0x3dd53d8e,0xbe000000,0x3ded3d44,0x3cc8bdfb,0xbd8e3dd5,0xbe00,0xbd443ded,0x3dfb3cc8,0xbdd5bd8e,0x3e000000,0xbdedbd44,0xbcc83dfb,0x3d8ebdd5,
0xbded3d44,0x3d8ebdd5,0xbdf5bd15,0x3da23dc6,0xbdb5bdb5,0x3cc83dfb,0x3de2bd71,0xbdffbc49,0x3e000000,0xbdd5bd8e,0xbd153df5,0x3dc6bda2,0xbdb53db5,0x3dfbbcc8,0xbd71bde2,0xbc493dff,
0xbe000000,0x3db5bdb5,0xbdedbd44,0x3d443ded,0xbe00,0xbdb53db5,0x3ded3d44,0xbd44bded,0x3e00,0x3db5bdb5,0xbdedbd44,0x3d443ded,0xbe00,0xbdb53db5,0x3ded3d44,0xbd44bded,
0xbdedbd44,0x3dd5bd8e,0xbde2bd71,0x3c493dff,0x3db5bdb5,0xbdfbbcc8,0x3d153df5,0x3da2bdc6,0xbe000000,0x3d8e3dd5,0x3d71bde2,0xbdff3c49,0x3db53db5,0x3cc8bdfb,0xbdf53d15,0x3dc63da2,
0xbdb5bdb5,0x3dedbd44,0xbdd5bd8e,0xbcc83dfb,0x3e000000,0xbd44bded,0xbd8e3dd5,0x3dfb3cc8,0xbe00,0xbded3d44,0x3dd53d8e,0x3cc8bdfb,0xbe000000,0x3d443ded,0x3d8ebdd5,0xbdfbbcc8,
0xbd44bded,0x3dfbbcc8,0xbdc6bda2,0xbd713de2,0x3db53db5,0x3d8ebdd5,0xbdff3c49,0x3d153df5,0x3e000000,0xbcc8bdfb,0xbda23dc6,0x3de23d71,0x3db5bdb5,0xbdd5bd8e,0x3c493dff,0x3df5bd15,
0xbe00,0x3e000000,0xbdb5bdb5,0xbdb53db5,0x3e00,0x3e000000,0xbdb5bdb5,0xbdb53db5,0x3e00,0x3e000000,0xbdb5bdb5,0xbdb53db5,0x3e00,0x3e000000,0xbdb5bdb5,0xbdb53db5,
0x3d44bded,0x3dfb3cc8,0xbda2bdc6,0xbde23d71,0xbdb53db5,0x3d8e3dd5,0x3c49bdff,0xbdf5bd15,0xbe000000,0xbcc83dfb,0x3dc6bda2,0xbd71bde2,0xbdb5bdb5,0xbdd53d8e,0x3dff3c49,0x3d15bdf5,
0x3db5bdb5,0x3ded3d44,0xbd8ebdd5,0xbdfb3cc8,0xbe000000,0xbd443ded,0x3dd5bd8e,0xbcc8bdfb,0xbe00,0xbdedbd44,0x3d8e3dd5,0x3dfbbcc8,0x3e000000,0x3d44bded,0xbdd53d8e,0x3cc83dfb,
0x3dedbd44,0x3dd53d8e,0xbd71bde2,0xbdffbc49,0xbdb5bdb5,0xbdfb3cc8,0x3df53d15,0x3dc6bda2,0x3e000000,0x3d8ebdd5,0xbde23d71,0xbc493dff,0xbdb53db5,0x3cc83dfb,0x3d15bdf5,0xbda2bdc6,
0x3e000000,0x3db53db5,0xbd44bded,0xbdedbd44,0xbe00,0xbdb5bdb5,0x3d443ded,0x3ded3d44,0x3e00,0x3db53db5,0xbd44bded,0xbdedbd44,0xbe00,0xbdb5bdb5,0x3d443ded,0x3ded3d44,
0x3ded3d44,0x3d8e3dd5,0xbd15bdf5,0xbdc6bda2,0x3db5bdb5,0x3cc8bdfb,0xbd713de2,0x3c493dff,0xbe000000,0xbdd53d8e,0x3df5bd15,0x3da2bdc6,0x3db53db5,0x3dfb3cc8,0xbde2bd71,0xbdff3c49,
0x3db53db5,0x3d443ded,0xbcc8bdfb,0xbd8ebdd5,0x3e000000,0x3dedbd44,0xbdfb3cc8,0xbdd53d8e,0xbe00,0xbd44bded,0x3cc83dfb,0x3d8e3dd5,0xbe000000,0xbded3d44,0x3dfbbcc8,0x3dd5bd8e,
0x3d443ded,0x3cc83dfb,0xbc49bdff,0xbd15bdf5,0x3db53db5,0x3dd53d8e,0xbdc6bda2,0xbde2bd71,0x3e000000,0x3dfbbcc8,0xbdff3c49,0xbdf53d15,0x3db5bdb5,0x3d8ebdd5,0xbda23dc6,0xbd713de2,
0x3d803d80,0x3e00,0x3e00,0x3e00,0x3e00,0x3e00,0x3e00,0x3e00,0x3e00,0x3e00,0x3e00,0x3e00,0x3e00,0x3e00,0x3e00,0x3e00,
0xbd803d80,0x3cc8bdfb,0x3c49bdff,0x3d15bdf5,0xbded3d44,0x3dd5bd8e,0x3dc6bda2,0x3de2bd71,0xbdedbd44,0x3dfb3cc8,0x3dff3c49,0x3df53d15,0xbd44bded,0x3d8e3dd5,0x3da23dc6,0x3d713de2,
0x3d803d80,0xbd443ded,0xbcc83dfb,0xbd8e3dd5,0xbdb5bdb5,0xbdedbd44,0xbdfbbcc8,0xbdd5bd8e,0x3db5bdb5,0x3d44bded,0x3cc8bdfb,0x3d8ebdd5,0x3db53db5,0x3ded3d44,0x3dfb3cc8,0x3dd53d8e,
0xbd803d80,0x3d8ebdd5,0x3d15bdf5,0x3dc6bda2,0x3d44bded,0x3cc83dfb,0x3d713de2,0xbc493dff,0x3d443ded,0xbdd5bd8e,0xbdf5bd15,0xbda2bdc6,0xbdedbd44,0x3dfbbcc8,0x3de2bd71,0x3dff3c49,
0x3d803d80,0xbdb53db5,0xbd443ded,0xbded3d44,0x3e000000,0x3db5bdb5,0x3d44bded,0x3dedbd44,0xbe000000,0xbdb53db5,0xbd443ded,0xbded3d44,0x3e000000,0x3db5bdb5,0x3d44bded,0x3dedbd44,
0xbd803d80,0x3dd5bd8e,0x3d71bde2,0x3dffbc49,0x3d443ded,0xbdfbbcc8,0xbdf53d15,0xbdc6bda2,0x3d44bded,0x3d8e3dd5,0x3de23d71,0x3c493dff,0xbded3d44,0x3cc8bdfb,0xbd15bdf5,0x3da2bdc6,
0x3d803d80,0xbded3d44,0xbd8e3dd5,0xbdfbbcc8,0xbdb53db5,0x3d443ded,0x3dd53d8e,0xbcc83dfb,0x3db53db5,0x3dedbd44,0x3d8ebdd5,0x3dfb3cc8,0x3db5bdb5,0xbd44bded,0xbdd5bd8e,0x3cc8bdfb,
0xbd803d80,0x3dfbbcc8,0x3da2bdc6,0x3de23d71,0xbdedbd44,0x3d8ebdd5,0xbc49bdff,0x3df5bd15,0xbded3d44,0xbcc8bdfb,0xbdc6bda2,0x3d71bde2,0xbd443ded,0xbdd5bd8e,0xbdff3c49,0xbd15bdf5,
0x3d803d80,0xbe000000,0xbdb53db5,0xbdb5bdb5,0xbe00,0xbe000000,0xbdb53db5,0xbdb5bdb5,0xbe00,0xbe000000,0xbdb53db5,0xbdb5bdb5,0xbe00,0xbe000000,0xbdb53db5,0xbdb5bdb5,
0xbd803d80,0x3dfb3cc8,0x3dc6bda2,0x3d713de2,0x3dedbd44,0x3d8e3dd5,0x3dff3c49,0xbd153df5,0x3ded3d44,0xbcc83dfb,0x3da23dc6,0xbde23d71,0x3d443ded,0xbdd53d8e,0xbc493dff,0xbdf5bd15,
0x3d803d80,0xbdedbd44,0xbdd53d8e,0xbcc8bdfb,0x3db53db5,0x3d44bded,0xbd8ebdd5,0x3dfbbcc8,0xbdb53db5,0x3ded3d44,0x3dd5bd8e,0x3cc83dfb,0xbdb5bdb5,0xbd443ded,0x3d8e3dd5,0xbdfb3cc8,
0xbd803d80,0x3dd53d8e,0x3de2bd71,0xbc493dff,0xbd443ded,0xbdfb3cc8,0xbd153df5,0xbda2bdc6,0xbd44bded,0x3d8ebdd5,0xbd71bde2,0x3dff3c49,0x3ded3d44,0x3cc83dfb,0x3df53d15,0xbdc63da2,
0x3d803d80,0xbdb5bdb5,0xbded3d44,0x3d44bded,0xbe000000,0x3db53db5,0x3dedbd44,0xbd443ded,0x3e000000,0xbdb5bdb5,0xbded3d44,0x3d44bded,0xbe000000,0x3db53db5,0x3dedbd44,0xbd443ded,
0xbd803d80,0x3d8e3dd5,0x3df5bd15,0xbda23dc6,0xbd44bded,0x3cc8bdfb,0xbde2bd71,0x3dffbc49,0xbd443ded,0xbdd53d8e,0x3d153df5,0xbdc6bda2,0x3dedbd44,0x3dfb3cc8,0x3d71bde2,0x3c493dff,
0x3d803d80,0xbd44bded,0xbdfb3cc8,0x3dd5bd8e,0x3db5bdb5,0xbded3d44,0x3cc83dfb,0xbd8ebdd5,0xbdb5bdb5,0x3d443ded,0x3dfbbcc8,0xbdd53d8e,0xbdb53db5,0x3dedbd44,0xbcc8bdfb,0x3d8e3dd5,
0xbd803d80,0x3cc83dfb,0x3dffbc49,0xbdf53d15,0x3ded3d44,0x3dd53d8e,0x3da2bdc6,0xbd713de2,0x3dedbd44,0x3dfbbcc8,0xbc49bdff,0x3d153df5,0x3d44bded,0x3d8ebdd5,0xbdc6bda2,0x3de23d71,
0x3d803d80,0xbe00,0xbe000000,0x3e000000,0x3e00,0xbe00,0xbe000000,0x3e000000,0x3e00,0xbe00,0xbe000000,0x3e000000,0x3e00,0xbe00,0xbe000000,0x3e000000,
0xbd803d80,0xbcc83dfb,0x3dff3c49,0xbdf5bd15,0xbded3d44,0xbdd53d8e,0x3da23dc6,0xbd71bde2,0xbdedbd44,0xbdfbbcc8,0xbc493dff,0x3d15bdf5,0xbd44bded,0xbd8ebdd5,0xbdc63da2,0x3de2bd71,
0x3d803d80,0x3d44bded,0xbdfbbcc8,0x3dd53d8e,0xbdb5bdb5,0x3ded3d44,0x3cc8bdfb,0xbd8e3dd5,0x3db5bdb5,0xbd443ded,0x3dfb3cc8,0xbdd5bd8e,0x3db53db5,0xbdedbd44,0xbcc83dfb,0x3d8ebdd5,
0xbd803d80,0xbd8e3dd5,0x3df53d15,0xbda2bdc6,0x3d44bded,0xbcc8bdfb,0xbde23d71,0x3dff3c49,0x3d443ded,0x3dd53d8e,0x3d15bdf5,0xbdc63da2,0xbdedbd44,0xbdfb3cc8,0x3d713de2,0x3c49bdff,
0x3d803d80,0x3db5bdb5,0xbdedbd44,0x3d443ded,0x3e000000,0xbdb53db5,0x3ded3d44,0xbd44bded,0xbe000000,0x3db5bdb5,0xbdedbd44,0x3d443ded,0x3e000000,0xbdb53db5,0x3ded3d44,0xbd44bded,
0xbd803d80,0xbdd53d8e,0x3de23d71,0xbc49bdff,0x3d443ded,0x3dfb3cc8,0xbd15bdf5,0xbda23dc6,0x3d44bded,0xbd8ebdd5,0xbd713de2,0x3dffbc49,0xbded3d44,0xbcc83dfb,0x3df5bd15,0xbdc6bda2,
0x3d803d80,0x3dedbd44,0xbdd5bd8e,0xbcc83dfb,0xbdb53db5,0xbd44bded,0xbd8e3dd5,0x3dfb3cc8,0x3db53db5,0xbded3d44,0x3dd53d8e,0x3cc8bdfb,0x3db5bdb5,0x3d443ded,0x3d8ebdd5,0xbdfbbcc8,
0xbd803d80,0xbdfb3cc8,0x3dc63da2,0x3d71bde2,0xbdedbd44,0xbd8e3dd5,0x3dffbc49,0xbd15bdf5,0xbded3d44,0x3cc83dfb,0x3da2bdc6,0xbde2bd71,0xbd443ded,0x3dd53d8e,0xbc49bdff,0xbdf53d15,
0x3d803d80,0x3e000000,0xbdb5bdb5,0xbdb53db5,0xbe00,0x3e000000,0xbdb5bdb5,0xbdb53db5,0xbe00,0x3e000000,0xbdb5bdb5,0xbdb53db5,0xbe00,0x3e000000,0xbdb5bdb5,0xbdb53db5,
0xbd803d80,0xbdfbbcc8,0x3da23dc6,0x3de2bd71,0x3dedbd44,0xbd8ebdd5,0xbc493dff,0x3df53d15,0x3ded3d44,0x3cc8bdfb,0xbdc63da2,0x3d713de2,0x3d443ded,0x3dd5bd8e,0xbdffbc49,0xbd153df5,
0x3d803d80,0x3ded3d44,0xbd8ebdd5,0xbdfb3cc8,0x3db53db5,0xbd443ded,0x3dd5bd8e,0xbcc8bdfb,0xbdb53db5,0xbdedbd44,0x3d8e3dd5,0x3dfbbcc8,0xbdb5bdb5,0x3d44bded,0xbdd53d8e,0x3cc83dfb,
0xbd803d80,0xbdd5bd8e,0x3d713de2,0x3dff3c49,0xbd443ded,0x3dfbbcc8,0xbdf5bd15,0xbdc63da2,0xbd44bded,0xbd8e3dd5,0x3de2bd71,0x3c49bdff,0x3ded3d44,0xbcc8bdfb,0xbd153df5,0x3da23dc6,
0x3d803d80,0x3db53db5,0xbd44bded,0xbdedbd44,0xbe000000,0xbdb5bdb5,0x3d443ded,0x3ded3d44,0x3e000000,0x3db53db5,0xbd44bded,0xbdedbd44,0xbe000000,0xbdb5bdb5,0x3d443ded,0x3ded3d44,
0xbd803d80,0xbd8ebdd5,0x3d153df5,0x3dc63da2,0xbd44bded,0xbcc83dfb,0x3d71bde2,0xbc49bdff,0xbd443ded,0x3dd5bd8e,0xbdf53d15,0xbda23dc6,0x3dedbd44,0xbdfbbcc8,0x3de23d71,0x3dffbc49,
0x3d803d80,0x3d443ded,0xbcc8bdfb,0xbd8ebdd5,0x3db5bdb5,0x3dedbd44,0xbdfb3cc8,0xbdd53d8e,0xbdb5bdb5,0xbd44bded,0x3cc83dfb,0x3d8e3dd5,0xbdb53db5,0xbded3d44,0x3dfbbcc8,0x3dd5bd8e,
0xbd803d80,0xbcc8bdfb,0x3c493dff,0x3d153df5,0x3ded3d44,0xbdd5bd8e,0x3dc63da2,0x3de23d71,0x3dedbd44,0xbdfb3cc8,0x3dffbc49,0x3df5bd15,0x3d44bded,0xbd8e3dd5,0x3da2bdc6,0x3d71bde2,
0xbc493dff,0xbbc93e00,0xbb493e00,0xbc173dff,0xbcc83dfb,0xbcf93df8,0xbce03dfa,0xbd093df7,0xbd443ded,0xbd5b3de7,0xbd4f3dea,0xbd663de5,0xbd8e3dd5,0xbd983dce,0xbd933dd1,0xbd9d3dca,
0xbd713de2,0xbcf93df8,0xbc7b3dfe,0xbd383def,0xbdd53d8e,0xbdf13d2c,0xbde53d66,0xbdfa3ce0,0xbdedbd44,0xbdcebd98,0xbddfbd7c,0xbdb9bdb1,0xbcc8bdfb,0x3bc9be00,0xbc17bdff,0x3cafbdfc,
0xbdc63da2,0xbd5b3de7,0xbce03dfa,0xbd9d3dca,0xbdfbbcc8,0xbdcebd98,0xbdeabd4f,0xbda7bdc2,0x3d44bded,0x3dbebdac,0x3d93bdd1,0x3ddfbd7c,0x3dd53d8e,0x3d843ddc,0x3db13db9,0x3d213df3,
0xbdf53d15,0xbd983dce,0xbd213df3,0xbdd13d93,0xbd8ebdd5,0x3bc9be00,0xbd09bdf7,0x3d38bdef,0x3ded3d44,0x3d843ddc,0x3dc23da7,0x3ce03dfa,0xbdfb3cc8,0xbde7bd5b,0xbdfebc7b,0xbdb9bdb1,
0xbdffbc49,0xbdbe3dac,0xbd4f3dea,0xbdf33d21,0x3cc8bdfb,0x3ddcbd84,0x3d93bdd1,0x3dfebc7b,0xbd443ded,0xbdf13d2c,0xbdb93db1,0xbdffbc17,0x3d8ebdd5,0x3dfdbc96,0x3dd8bd89,0x3df73d09,
0xbde2bd71,0xbddc3d84,0xbd7c3ddf,0xbe003b49,0x3dd5bd8e,0x3de73d5b,0x3dffbc17,0x3d933dd1,0xbdedbd44,0xbc96bdfd,0xbd9dbdca,0x3d38bdef,0x3cc83dfb,0xbdbe3dac,0xbd213df3,0xbdfa3ce0,
0xbda2bdc6,0xbdf13d2c,0xbd933dd1,0xbdf7bd09,0x3dfb3cc8,0x3c963dfd,0x3db13db9,0xbd663de5,0x3d44bded,0x3e003bc9,0x3dd8bd89,0x3dca3d9d,0xbdd5bd8e,0x3cf9bdf8,0xbd38bdef,0x3dc2bda7,
0xbd15bdf5,0xbdfd3c96,0xbda73dc2,0xbdd8bd89,0x3d8e3dd5,0xbdbe3dac,0xbc7b3dfe,0xbe003b49,0x3ded3d44,0xbcf93df8,0x3d663de5,0xbdd13d93,0x3dfbbcc8,0x3d2c3df1,0x3ddf3d7c,0xbd383def,
0x3c49bdff,0xbe00bbc9,0xbdb93db1,0xbda7bdc2,0xbcc83dfb,0xbdf8bcf9,0xbdd83d89,0xbd7cbddf,0xbd443ded,0xbde7bd5b,0xbdef3d38,0xbd21bdf3,0xbd8e3dd5,0xbdcebd98,0xbdfc3caf,0xbc7bbdfe,
0x3d71bde2,0xbdf8bcf9,0xbdca3d9d,0xbd4fbdea,0xbdd53d8e,0xbd2cbdf1,0xbdf3bd21,0x3d89bdd8,0xbdedbd44,0x3d98bdce,0xbd09bdf7,0x3e00bb49,0xbcc8bdfb,0x3e003bc9,0x3da7bdc2,0x3d933dd1,
0x3dc6bda2,0xbde7bd5b,0xbdd83d89,0xbc7bbdfe,0xbdfbbcc8,0x3d98bdce,0xbd38bdef,0x3dff3c17,0x3d44bded,0x3dac3dbe,0x3dfcbcaf,0xbd093df7,0x3dd53d8e,0xbddc3d84,0xbb493e00,0xbde5bd66,
0x3df5bd15,0xbdcebd98,0xbde53d66,0x3cafbdfc,0xbd8ebdd5,0x3e003bc9,0x3d7cbddf,0x3d4f3dea,0x3ded3d44,0xbddc3d84,0x3c173dff,0xbdd8bd89,0xbdfb3cc8,0x3d5bbde7,0xbd9dbdca,0x3e00bb49,
0x3dff3c49,0xbdacbdbe,0xbdef3d38,0x3d66bde5,0x3cc8bdfb,0x3d843ddc,0x3dfcbcaf,0xbd9d3dca,0xbd443ded,0xbd2cbdf1,0xbe00bb49,0x3dc2bda7,0x3d8ebdd5,0x3c963dfd,0x3dfa3ce0,0xbddf3d7c,
0x3de23d71,0xbd84bddc,0xbdf73d09,0x3db1bdb9,0x3dd5bd8e,0xbd5b3de7,0x3dc23da7,0xbdfcbcaf,0xbdedbd44,0x3dfdbc96,0x3c7bbdfe,0x3d4f3dea,0x3cc83dfb,0xbdacbdbe,0xbde53d66,0x3d89bdd8,
0x3da23dc6,0xbd2cbdf1,0xbdfc3caf,0x3ddfbd7c,0x3dfb3cc8,0xbdfd3c96,0xbb493e00,0xbd21bdf3,0x3d44bded,0xbbc93e00,0x3dfa3ce0,0xbdfe3c7b,0xbdd5bd8e,0x3df83cf9,0x3d4fbdea,0xbc173dff,
0x3d153df5,0xbc96bdfd,0xbdff3c17,0x3dfabce0,0x3d8e3dd5,0xbdacbdbe,0xbdca3d9d,0x3db1bdb9,0x3ded3d44,0xbdf8bcf9,0xbd213df3,0x3cafbdfc,0x3dfbbcc8,0xbdf13d2c,0x3d093df7,0xbd4fbdea,
0xbc493dff,0x3bc9be00,0xbe00bb49,0x3dff3c17,0xbcc83dfb,0x3cf9bdf8,0xbdfabce0,0x3df73d09,0xbd443ded,0x3d5bbde7,0xbdeabd4f,0x3de53d66,0xbd8e3dd5,0x3d98bdce,0xbdd1bd93,0x3dca3d9d,
0xbd713de2,0x3cf9bdf8,0xbdfebc7b,0x3def3d38,0xbdd53d8e,0x3df1bd2c,0xbd66bde5,0x3ce03dfa,0xbdedbd44,0x3dce3d98,0x3d7cbddf,0xbdb13db9,0xbcc8bdfb,0xbbc93e00,0x3dffbc17,0xbdfcbcaf,
0xbdc63da2,0x3d5bbde7,0xbdfabce0,0x3dca3d9d,0xbdfbbcc8,0x3dce3d98,0x3d4fbdea,0xbdc23da7,0x3d44bded,0xbdbe3dac,0x3dd13d93,0xbd7cbddf,0x3dd53d8e,0xbd84bddc,0xbdb93db1,0x3df3bd21,
0xbdf53d15,0x3d98bdce,0xbdf3bd21,0x3d933dd1,0xbd8ebdd5,0xbbc93e00,0x3df7bd09,0xbdefbd38,0x3ded3d44,0xbd84bddc,0xbda73dc2,0x3dfabce0,0xbdfb3cc8,0x3de73d5b,0x3c7bbdfe,0xbdb13db9,
0xbdffbc49,0x3dbebdac,0xbdeabd4f,0x3d213df3,0x3cc8bdfb,0xbddc3d84,0x3dd13d93,0xbc7bbdfe,0xbd443ded,0x3df1bd2c,0xbdb1bdb9,0xbc173dff,0x3d8ebdd5,0xbdfd3c96,0x3d893dd8,0x3d09bdf7,
0xbde2bd71,0x3ddcbd84,0xbddfbd7c,0x3b493e00,0x3dd5bd8e,0xbde7bd5b,0x3c173dff,0x3dd1bd93,0xbdedbd44,0x3c963dfd,0x3dcabd9d,0xbdefbd38,0x3cc83dfb,0x3dbebdac,0xbdf3bd21,0x3ce03dfa,
0xbda2bdc6,0x3df1bd2c,0xbdd1bd93,0xbd093df7,0x3dfb3cc8,0xbc96bdfd,0xbdb93db1,0x3de53d66,0x3d44bded,0xbe00bbc9,0x3d893dd8,0x3d9dbdca,0xbdd5bd8e,0xbcf93df8,0x3defbd38,0xbda7bdc2,
0xbd15bdf5,0x3dfdbc96,0xbdc2bda7,0xbd893dd8,0x3d8e3dd5,0x3dbebdac,0xbdfebc7b,0x3b493e00,0x3ded3d44,0x3cf9bdf8,0xbde53d66,0x3d933dd1,0x3dfbbcc8,0xbd2cbdf1,0xbd7c3ddf,0x3def3d38,
0x3c49bdff,0x3e003bc9,0xbdb1bdb9,0xbdc23da7,0xbcc83dfb,0x3df83cf9,0xbd89bdd8,0xbddf3d7c,0xbd443ded,0x3de73d5b,0xbd38bdef,0xbdf33d21,0xbd8e3dd5,0x3dce3d98,0xbcafbdfc,0xbdfe3c7b,
0x3d71bde2,0x3df83cf9,0xbd9dbdca,0xbdea3d4f,0xbdd53d8e,0x3d2c3df1,0x3d21bdf3,0xbdd8bd89,0xbdedbd44,0xbd983dce,0x3df7bd09,0xbb49be00,0xbcc8bdfb,0xbe00bbc9,0x3dc23da7,0x3dd1bd93,
0x3dc6bda2,0x3de73d5b,0xbd89bdd8,0xbdfe3c7b,0xbdfbbcc8,0xbd983dce,0x3defbd38,0x3c17bdff,0x3d44bded,0xbdacbdbe,0x3caf3dfc,0x3df73d09,0x3dd53d8e,0x3ddcbd84,0xbe00bb49,0xbd663de5,
0x3df5bd15,0x3dce3d98,0xbd66bde5,0xbdfcbcaf,0xbd8ebdd5,0xbe00bbc9,0x3ddf3d7c,0x3deabd4f,0x3ded3d44,0x3ddcbd84,0xbdff3c17,0xbd893dd8,0xbdfb3cc8,0xbd5b3de7,0x3dcabd9d,0xbb49be00,
0x3dff3c49,0x3dac3dbe,0xbd38bdef,0xbde5bd66,0x3cc8bdfb,0xbd84bddc,0x3caf3dfc,0x3dca3d9d,0xbd443ded,0x3d2c3df1,0x3b49be00,0xbda7bdc2,0x3d8ebdd5,0xbc96bdfd,0xbce03dfa,0x3d7c3ddf,
0x3de23d71,0x3d843ddc,0xbd09bdf7,0xbdb9bdb1,0x3dd5bd8e,0x3d5bbde7,0xbda73dc2,0xbcaf3dfc,0xbdedbd44,0xbdfd3c96,0x3dfe3c7b,0x3deabd4f,0x3cc83dfb,0x3dac3dbe,0xbd66bde5,0xbdd8bd89,
0x3da23dc6,0x3d2c3df1,0xbcafbdfc,0xbd7cbddf,0x3dfb3cc8,0x3dfdbc96,0xbe00bb49,0xbdf33d21,0x3d44bded,0x3bc9be00,0xbce03dfa,0x3c7b3dfe,0xbdd5bd8e,0xbdf8bcf9,0x3dea3d4f,0x3dff3c17,
0x3d153df5,0x3c963dfd,0xbc17bdff,0xbce0bdfa,0x3d8e3dd5,0x3dac3dbe,0xbd9dbdca,0xbdb9bdb1,0x3ded3d44,0x3df83cf9,0xbdf3bd21,0xbdfcbcaf,0x3dfbbcc8,0x3df1bd2c,0xbdf73d09,0xbdea3d4f,
0xbdb53d80,0xbdbe3dac,0xbdb93db1,0xbdc23da7,0xbd153df5,0xbddc3d84,0xbdd83d89,0xbddf3d7c,0xbd713de2,0xbdf13d2c,0xbdef3d38,0xbdf33d21,0xbda23dc6,0xbdfd3c96,0xbdfc3caf,0xbdfe3c7b,
0x3db53d80,0x3ddcbd84,0x3dcabd9d,0x3deabd4f,0xbdff3c49,0x3de73d5b,0x3df33d21,0x3dd83d89,0xbda2bdc6,0x3c963dfd,0x3d093df7,0x3b493e00,0x3d15bdf5,0xbdbe3dac,0xbda73dc2,0xbdd13d93,
0xbdb53d80,0xbdf13d2c,0xbdd83d89,0xbdfe3c7b,0xbd71bde2,0xbc96bdfd,0xbd38bdef,0x3c17bdff,0x3df5bd15,0x3e003bc9,0x3dfcbcaf,0x3df73d09,0x3c493dff,0xbcf93df8,0xbb493e00,0xbd663de5,
0x3db53d80,0x3dfdbc96,0x3de5bd66,0x3dfc3caf,0x3da2bdc6,0xbdbe3dac,0xbd7c3ddf,0xbdea3d4f,0xbc493dff,0x3cf9bdf8,0xbc17bdff,0x3d89bdd8,0xbd71bde2,0x3d2c3df1,0x3d9d3dca,0x3b493e00,
0xbdb53d80,0xbe00bbc9,0xbdef3d38,0xbde5bd66,0x3df53d15,0x3df83cf9,0x3dfcbcaf,0x3dca3d9d,0xbde2bd71,0xbde7bd5b,0xbe00bb49,0xbda7bdc2,0x3dc63da2,0x3dce3d98,0x3dfa3ce0,0x3d7c3ddf,
0x3db53d80,0x3df83cf9,0x3df7bd09,0x3db93db1,0x3c493dff,0xbd2cbdf1,0xbdc2bda7,0x3cafbdfc,0x3dc6bda2,0xbd983dce,0xbc7b3dfe,0xbdea3d4f,0xbdf5bd15,0x3e003bc9,0x3de5bd66,0x3dd83d89,
0xbdb53d80,0xbde7bd5b,0xbdfc3caf,0xbd7cbddf,0xbde23d71,0xbd983dce,0xbb493e00,0xbdf33d21,0x3d153df5,0x3dac3dbe,0x3dfa3ce0,0x3c7b3dfe,0x3dffbc49,0x3ddcbd84,0x3d4fbdea,0x3dff3c17,
0x3db53d80,0x3dce3d98,0x3dffbc17,0x3ce03dfa,0xbdc6bda2,0x3e003bc9,0x3dcabd9d,0x3db93db1,0xbdffbc49,0x3ddcbd84,0x3d21bdf3,0x3dfc3caf,0xbde23d71,0x3d5bbde7,0xbd09bdf7,0x3deabd4f,
0xbdb53d80,0xbdacbdbe,0xbe00bb49,0x3c17bdff,0x3d15bdf5,0xbd84bddc,0xbdfabce0,0x3d09bdf7,0x3d71bde2,0xbd2cbdf1,0xbdeabd4f,0x3d66bde5,0x3da2bdc6,0xbc96bdfd,0xbdd1bd93,0x3d9dbdca,
0x3db53d80,0x3d843ddc,0x3dfe3c7b,0xbd383def,0x3dffbc49,0xbd5b3de7,0x3d663de5,0xbdfa3ce0,0x3da23dc6,0xbdfd3c96,0xbd7c3ddf,0xbdb9bdb1,0xbd153df5,0xbdacbdbe,0xbdff3c17,0x3cafbdfc,
0xbdb53d80,0xbd2cbdf1,0xbdfabce0,0x3d9dbdca,0x3d713de2,0x3dfdbc96,0x3d4fbdea,0x3da73dc2,0xbdf53d15,0xbbc93e00,0x3dd13d93,0xbddf3d7c,0xbc49bdff,0xbdf8bcf9,0xbdb93db1,0xbd21bdf3,
0x3db53d80,0x3c963dfd,0x3df33d21,0xbdd13d93,0xbda23dc6,0xbdacbdbe,0xbdf73d09,0x3d38bdef,0x3c49bdff,0x3df83cf9,0x3da7bdc2,0x3ce03dfa,0x3d713de2,0xbdf13d2c,0xbc7b3dfe,0xbdb9bdb1,
0xbdb53d80,0x3bc9be00,0xbdeabd4f,0x3df3bd21,0xbdf5bd15,0xbcf93df8,0x3dd13d93,0xbdfe3c7b,0x3de23d71,0x3d5bbde7,0xbdb1bdb9,0x3dff3c17,0xbdc6bda2,0xbd983dce,0x3d893dd8,0xbdf7bd09,
0x3db53d80,0xbcf93df8,0x3ddf3d7c,0xbe003b49,0xbc49bdff,0x3df1bd2c,0xbc17bdff,0x3d933dd1,0xbdc63da2,0xbdcebd98,0xbdca3d9d,0x3d38bdef,0x3df53d15,0xbbc93e00,0x3df33d21,0xbdfa3ce0,
0xbdb53d80,0x3d5bbde7,0xbdd1bd93,0x3df73d09,0x3de2bd71,0xbdcebd98,0xbdb93db1,0x3d66bde5,0xbd15bdf5,0xbdbe3dac,0x3d893dd8,0xbdcabd9d,0xbdff3c49,0x3d843ddc,0x3defbd38,0xbdc23da7,
0x3db53d80,0xbd983dce,0x3dc23da7,0xbdd8bd89,0x3dc63da2,0xbbc93e00,0x3dfe3c7b,0xbe003b49,0x3dff3c49,0x3d843ddc,0x3de5bd66,0xbdd13d93,0x3de2bd71,0x3de73d5b,0x3d7cbddf,0xbd383def,
0xbdb53d80,0x3dbebdac,0xbdb1bdb9,0x3da73dc2,0xbd153df5,0x3ddcbd84,0xbd89bdd8,0x3d7c3ddf,0xbd713de2,0x3df1bd2c,0xbd38bdef,0x3d213df3,0xbda23dc6,0x3dfdbc96,0xbcafbdfc,0x3c7b3dfe,
0x3db53d80,0xbddc3d84,0x3d9d3dca,0xbd4fbdea,0xbdff3c49,0xbde7bd5b,0xbd213df3,0x3d89bdd8,0xbda2bdc6,0xbc96bdfd,0xbdf73d09,0x3e00bb49,0x3d15bdf5,0x3dbebdac,0xbdc2bda7,0x3d933dd1,
0xbdb53d80,0x3df1bd2c,0xbd89bdd8,0x3c7b3dfe,0xbd71bde2,0x3c963dfd,0x3defbd38,0xbdffbc17,0x3df5bd15,0xbe00bbc9,0x3caf3dfc,0x3d09bdf7,0x3c493dff,0x3cf9bdf8,0xbe00bb49,0x3de53d66,
0x3db53d80,0xbdfd3c96,0x3d663de5,0x3cafbdfc,0x3da2bdc6,0x3dbebdac,0xbddfbd7c,0x3d4f3dea,0xbc493dff,0xbcf93df8,0x3dffbc17,0xbdd8bd89,0xbd71bde2,0xbd2cbdf1,0xbdca3d9d,0x3e00bb49,
0xbdb53d80,0x3e003bc9,0xbd38bdef,0xbd663de5,0x3df53d15,0xbdf8bcf9,0x3caf3dfc,0x3d9dbdca,0xbde2bd71,0x3de73d5b,0x3b49be00,0xbdc23da7,0x3dc63da2,0xbdcebd98,0xbce03dfa,0x3ddfbd7c,
0x3db53d80,0xbdf8bcf9,0x3d093df7,0x3db1bdb9,0x3c493dff,0x3d2c3df1,0x3da7bdc2,0xbdfcbcaf,0x3dc6bda2,0x3d98bdce,0xbdfebc7b,0x3d4f3dea,0xbdf5bd15,0xbe00bbc9,0x3d663de5,0x3d89bdd8,
0xbdb53d80,0x3de73d5b,0xbcafbdfc,0xbddf3d7c,0xbde23d71,0x3d98bdce,0xbe00bb49,0x3d213df3,0x3d153df5,0xbdacbdbe,0xbce03dfa,0x3dfebc7b,0x3dffbc49,0xbddc3d84,0x3dea3d4f,0x3c17bdff,
0x3db53d80,0xbdcebd98,0x3c173dff,0x3dfabce0,0xbdc6bda2,0xbe00bbc9,0x3d9d3dca,0x3db1bdb9,0xbdffbc49,0xbddc3d84,0x3df33d21,0x3cafbdfc,0xbde23d71,0xbd5b3de7,0x3df7bd09,0xbd4fbdea,
0xbdb53d80,0x3dac3dbe,0x3b49be00,0xbdffbc17,0x3d15bdf5,0x3d843ddc,0x3ce0bdfa,0xbdf7bd09,0x3d71bde2,0x3d2c3df1,0x3d4fbdea,0xbde5bd66,0x3da2bdc6,0x3c963dfd,0x3d93bdd1,0xbdcabd9d,
0x3db53d80,0xbd84bddc,0xbc7b3dfe,0x3def3d38,0x3dffbc49,0x3d5bbde7,0xbde53d66,0x3ce03dfa,0x3da23dc6,0x3dfdbc96,0xbddfbd7c,0xbdb13db9,0xbd153df5,0x3dac3dbe,0xbc17bdff,0xbdfcbcaf,
0xbdb53d80,0x3d2c3df1,0x3ce0bdfa,0xbdcabd9d,0x3d713de2,0xbdfd3c96,0x3dea3d4f,0x3dc2bda7,0xbdf53d15,0x3bc9be00,0xbd933dd1,0x3d7c3ddf,0xbc49bdff,0x3df83cf9,0xbdb1bdb9,0xbdf33d21,
0x3db53d80,0xbc96bdfd,0xbd213df3,0x3d933dd1,0xbda23dc6,0x3dac3dbe,0xbd09bdf7,0xbdefbd38,0x3c49bdff,0xbdf8bcf9,0x3dc23da7,0x3dfabce0,0x3d713de2,0x3df1bd2c,0xbdfebc7b,0xbdb13db9,
0xbdb53d80,0xbbc93e00,0x3d4fbdea,0xbd21bdf3,0xbdf5bd15,0x3cf9bdf8,0xbd933dd1,0x3c7b3dfe,0x3de23d71,0xbd5b3de7,0x3db9bdb1,0x3c17bdff,0xbdc6bda2,0x3d98bdce,0xbdd83d89,0xbd093df7,
0x3db53d80,0x3cf9bdf8,0xbd7c3ddf,0x3b493e00,0xbc49bdff,0xbdf13d2c,0x3dffbc17,0x3dd1bd93,0xbdc63da2,0x3dce3d98,0xbd9dbdca,0xbdefbd38,0x3df53d15,0x3bc9be00,0xbd213df3,0x3ce03dfa,
0xbdb53d80,0xbd5b3de7,0x3d93bdd1,0x3d09bdf7,0x3de2bd71,0x3dce3d98,0xbdb1bdb9,0xbde5bd66,0xbd15bdf5,0x3dbebdac,0xbdd83d89,0xbd9d3dca,0xbdff3c49,0xbd84bddc,0x3d383def,0x3da73dc2,
0x3db53d80,0x3d98bdce,0xbda73dc2,0xbd893dd8,0x3dc63da2,0x3bc9be00,0xbc7b3dfe,0x3b493e00,0x3dff3c49,0xbd84bddc,0x3d663de5,0x3d933dd1,0x3de2bd71,0xbde7bd5b,0x3ddf3d7c,0x3def3d38,
0xbcc83dfb,0xbc493dff,0xbbc93e00,0xbc963dfd,0xbd443ded,0xbd713de2,0xbd5b3de7,0xbd843ddc,0xbdb53db5,0xbdc63da2,0xbdbe3dac,0xbdce3d98,0xbded3d44,0xbdf53d15,0xbdf13d2c,0xbdf83cf9,
0xbd8e3dd5,0xbd153df5,0xbc963dfd,0xbd5b3de7,0xbded3d44,0xbdff3c49,0xbdf83cf9,0xbe00bbc9,0xbdb5bdb5,0xbd71bde2,0xbd98bdce,0xbd2cbdf1,0x3d44bded,0x3da2bdc6,0x3d84bddc,0x3dbebdac,
0xbdd53d8e,0xbd713de2,0xbcf93df8,0xbdac3dbe,0xbdedbd44,0xbda2bdc6,0xbdcebd98,0xbd5bbde7,0x3db5bdb5,0x3df5bd15,0x3ddcbd84,0x3e00bbc9,0x3d443ded,0xbc493dff,0x3c963dfd,0xbd2c3df1,
0xbdfb3cc8,0xbda23dc6,0xbd2c3df1,0xbddc3d84,0xbd44bded,0x3d15bdf5,0xbbc9be00,0x3d98bdce,0x3db53db5,0x3c493dff,0x3d5b3de7,0xbcf93df8,0xbdedbd44,0xbd71bde2,0xbdbebdac,0xbc96bdfd,
0xbdfbbcc8,0xbdc63da2,0xbd5b3de7,0xbdf83cf9,0x3d44bded,0x3df5bd15,0x3dbebdac,0x3dfd3c96,0xbdb53db5,0xbdffbc49,0xbdf13d2c,0xbddcbd84,0x3dedbd44,0x3de23d71,0x3e003bc9,0x3d983dce,
0xbdd5bd8e,0xbde23d71,0xbd843ddc,0xbe00bbc9,0x3dedbd44,0x3dc63da2,0x3dfd3c96,0x3d2c3df1,0xbdb5bdb5,0x3d15bdf5,0xbcf9bdf8,0x3dbebdac,0xbd443ded,0xbdff3c49,0xbdce3d98,0xbde7bd5b,
0xbd8ebdd5,0xbdf53d15,0xbd983dce,0xbdf1bd2c,0x3ded3d44,0xbc493dff,0x3d843ddc,0xbdac3dbe,0x3db5bdb5,0x3de23d71,0x3dfdbc96,0x3d5b3de7,0xbd44bded,0x3dc6bda2,0x3cf9bdf8,0x3e00bbc9,
0xbcc8bdfb,0xbdff3c49,0xbdac3dbe,0xbdcebd98,0x3d443ded,0xbde23d71,0xbd2c3df1,0xbdf8bcf9,0x3db53db5,0xbda23dc6,0x3bc93e00,0xbdfd3c96,0x3ded3d44,0xbd153df5,0x3d5b3de7,0xbddc3d84,
0x3cc8bdfb,0xbdffbc49,0xbdbe3dac,0xbd98bdce,0xbd443ded,0xbde2bd71,0xbdf13d2c,0xbcf9bdf8,0xbdb53db5,0xbda2bdc6,0xbe00bbc9,0x3c96bdfd,0xbded3d44,0xbd15bdf5,0xbde7bd5b,0x3d84bddc,
0x3d8ebdd5,0xbdf5bd15,0xbdce3d98,0xbd2cbdf1,0xbded3d44,0xbc49bdff,0xbddcbd84,0x3dbebdac,0xbdb5bdb5,0x3de2bd71,0x3c96bdfd,0x3de73d5b,0x3d44bded,0x3dc63da2,0x3df8bcf9,0xbbc93e00,
0x3dd5bd8e,0xbde2bd71,0xbddc3d84,0xbbc9be00,0xbdedbd44,0x3dc6bda2,0xbc96bdfd,0x3df13d2c,0x3db5bdb5,0x3d153df5,0x3df83cf9,0xbdac3dbe,0x3d443ded,0xbdffbc49,0xbd983dce,0xbd5bbde7,
0x3dfbbcc8,0xbdc6bda2,0xbde73d5b,0x3cf9bdf8,0xbd44bded,0x3df53d15,0x3dacbdbe,0x3c963dfd,0x3db53db5,0xbdff3c49,0xbd2c3df1,0xbd84bddc,0xbdedbd44,0x3de2bd71,0xbbc9be00,0x3dce3d98,
0x3dfb3cc8,0xbda2bdc6,0xbdf13d2c,0x3d84bddc,0x3d44bded,0x3d153df5,0x3e003bc9,0xbdce3d98,0xbdb53db5,0x3c49bdff,0xbde7bd5b,0x3df8bcf9,0x3dedbd44,0xbd713de2,0x3dac3dbe,0xbdfdbc96,
0x3dd53d8e,0xbd71bde2,0xbdf83cf9,0x3dbebdac,0x3dedbd44,0xbda23dc6,0x3d983dce,0xbde7bd5b,0xbdb5bdb5,0x3df53d15,0x3d84bddc,0xbbc93e00,0xbd443ded,0xbc49bdff,0xbdfdbc96,0x3df1bd2c,
0x3d8e3dd5,0xbd15bdf5,0xbdfd3c96,0x3de7bd5b,0x3ded3d44,0xbdffbc49,0xbcf93df8,0xbbc9be00,0x3db5bdb5,0xbd713de2,0x3dce3d98,0xbdf1bd2c,0xbd44bded,0x3da23dc6,0x3ddcbd84,0xbdac3dbe,
0x3cc83dfb,0xbc49bdff,0xbe003bc9,0x3dfdbc96,0x3d443ded,0xbd71bde2,0xbde73d5b,0x3ddcbd84,0x3db53db5,0xbdc6bda2,0xbdac3dbe,0x3d98bdce,0x3ded3d44,0xbdf5bd15,0xbd2c3df1,0x3cf9bdf8,
0xbcc83dfb,0x3c49bdff,0xbe00bbc9,0x3dfd3c96,0xbd443ded,0x3d71bde2,0xbde7bd5b,0x3ddc3d84,0xbdb53db5,0x3dc6bda2,0xbdacbdbe,0x3d983dce,0xbded3d44,0x3df5bd15,0xbd2cbdf1,0x3cf93df8,
0xbd8e3dd5,0x3d15bdf5,0xbdfdbc96,0x3de73d5b,0xbded3d44,0x3dffbc49,0xbcf9bdf8,0xbbc93e00,0xbdb5bdb5,0x3d713de2,0x3dcebd98,0xbdf13d2c,0x3d44bded,0xbda23dc6,0x3ddc3d84,0xbdacbdbe,
0xbdd53d8e,0x3d71bde2,0xbdf8bcf9,0x3dbe3dac,0xbdedbd44,0x3da23dc6,0x3d98bdce,0xbde73d5b,0x3db5bdb5,0xbdf53d15,0x3d843ddc,0xbbc9be00,0x3d443ded,0x3c49bdff,0xbdfd3c96,0x3df13d2c,
0xbdfb3cc8,0x3da2bdc6,0xbdf1bd2c,0x3d843ddc,0xbd44bded,0xbd153df5,0x3e00bbc9,0xbdcebd98,0x3db53db5,0xbc49bdff,0xbde73d5b,0x3df83cf9,0xbdedbd44,0x3d713de2,0x3dacbdbe,0xbdfd3c96,
0xbdfbbcc8,0x3dc6bda2,0xbde7bd5b,0x3cf93df8,0x3d44bded,0xbdf53d15,0x3dac3dbe,0x3c96bdfd,0xbdb53db5,0x3dff3c49,0xbd2cbdf1,0xbd843ddc,0x3dedbd44,0xbde2bd71,0xbbc93e00,0x3dcebd98,
0xbdd5bd8e,0x3de2bd71,0xbddcbd84,0xbbc93e00,0x3dedbd44,0xbdc6bda2,0xbc963dfd,0x3df1bd2c,0xbdb5bdb5,0xbd153df5,0x3df8bcf9,0xbdacbdbe,0xbd443ded,0x3dffbc49,0xbd98bdce,0xbd5b3de7,
0xbd8ebdd5,0x3df5bd15,0xbdcebd98,0xbd2c3df1,0x3ded3d44,0x3c49bdff,0xbddc3d84,0x3dbe3dac,0x3db5bdb5,0xbde2bd71,0x3c963dfd,0x3de7bd5b,0xbd44bded,0xbdc63da2,0x3df83cf9,0xbbc9be00,
0xbcc8bdfb,0x3dffbc49,0xbdbebdac,0xbd983dce,0x3d443ded,0x3de2bd71,0xbdf1bd2c,0xbcf93df8,0x3db53db5,0x3da2bdc6,0xbe003bc9,0x3c963dfd,0x3ded3d44,0x3d15bdf5,0xbde73d5b,0x3d843ddc,
0x3cc8bdfb,0x3dff3c49,0xbdacbdbe,0xbdce3d98,0xbd443ded,0x3de23d71,0xbd2cbdf1,0xbdf83cf9,0xbdb53db5,0x3da23dc6,0x3bc9be00,0xbdfdbc96,0xbded3d44,0x3d153df5,0x3d5bbde7,0xbddcbd84,
0x3d8ebdd5,0x3df53d15,0xbd98bdce,0xbdf13d2c,0xbded3d44,0x3c493dff,0x3d84bddc,0xbdacbdbe,0xbdb5bdb5,0xbde23d71,0x3dfd3c96,0x3d5bbde7,0x3d44bded,0xbdc6bda2,0x3cf93df8,0x3e003bc9,
0x3dd5bd8e,0x3de23d71,0xbd84bddc,0xbe003bc9,0xbdedbd44,0xbdc63da2,0x3dfdbc96,0x3d2cbdf1,0x3db5bdb5,0xbd15bdf5,0xbcf93df8,0x3dbe3dac,0x3d443ded,0x3dff3c49,0xbdcebd98,0xbde73d5b,
0x3dfbbcc8,0x3dc63da2,0xbd5bbde7,0xbdf8bcf9,0xbd44bded,0xbdf5bd15,0x3dbe3dac,0x3dfdbc96,0x3db53db5,0x3dffbc49,0xbdf1bd2c,0xbddc3d84,0xbdedbd44,0xbde23d71,0x3e00bbc9,0x3d98bdce,
0x3dfb3cc8,0x3da23dc6,0xbd2cbdf1,0xbddcbd84,0x3d44bded,0xbd15bdf5,0xbbc93e00,0x3d983dce,0xbdb53db5,0xbc493dff,0x3d5bbde7,0xbcf9bdf8,0x3dedbd44,0x3d71bde2,0xbdbe3dac,0xbc963dfd,
0x3dd53d8e,0x3d713de2,0xbcf9bdf8,0xbdacbdbe,0x3dedbd44,0x3da2bdc6,0xbdce3d98,0xbd5b3de7,0xbdb5bdb5,0xbdf5bd15,0x3ddc3d84,0x3e003bc9,0xbd443ded,0x3c493dff,0x3c96bdfd,0xbd2cbdf1,
0x3d8e3dd5,0x3d153df5,0xbc96bdfd,0xbd5bbde7,0x3ded3d44,0x3dff3c49,0xbdf8bcf9,0xbe003bc9,0x3db5bdb5,0x3d71bde2,0xbd983dce,0xbd2c3df1,0xbd44bded,0xbda2bdc6,0x3d843ddc,0x3dbe3dac,
0x3cc83dfb,0x3c493dff,0xbbc9be00,0xbc96bdfd,0x3d443ded,0x3d713de2,0xbd5bbde7,0xbd84bddc,0x3db53db5,0x3dc63da2,0xbdbebdac,0xbdcebd98,0x3ded3d44,0x3df53d15,0xbdf1bd2c,0xbdf8bcf9,
0xbd803d80,0xbdffbc49,0xbe00bbc9,0xbdfdbc96,0xbd8e3dd5,0xbde2bd71,0xbde7bd5b,0xbddcbd84,0xbdd53d8e,0xbda2bdc6,0xbdacbdbe,0xbd98bdce,0xbdfb3cc8,0xbd15bdf5,0xbd2cbdf1,0xbcf9bdf8,
0x3d803d80,0x3df53d15,0x3dfd3c96,0x3de73d5b,0xbdfbbcc8,0x3c493dff,0x3cf93df8,0xbbc93e00,0xbcc8bdfb,0xbde23d71,0xbdce3d98,0xbdf13d2c,0x3dd5bd8e,0xbdc6bda2,0xbddcbd84,0xbdacbdbe,
0xbd803d80,0xbde2bd71,0xbdf8bcf9,0xbdbebdac,0xbcc8bdfb,0x3dc6bda2,0x3d98bdce,0x3de7bd5b,0x3dfb3cc8,0x3d153df5,0x3d843ddc,0x3bc93e00,0xbd8e3dd5,0xbdffbc49,0xbdfd3c96,0xbdf1bd2c,
0x3d803d80,0x3dc63da2,0x3df13d2c,0x3d843ddc,0x3dd5bd8e,0xbdf5bd15,0xbe003bc9,0xbdcebd98,0xbd8e3dd5,0x3dffbc49,0x3de7bd5b,0x3df83cf9,0x3cc8bdfb,0xbde23d71,0xbdac3dbe,0xbdfd3c96,
0xbd803d80,0xbda2bdc6,0xbde7bd5b,0xbcf9bdf8,0x3dd53d8e,0x3d153df5,0x3dac3dbe,0xbc963dfd,0xbd8ebdd5,0x3c49bdff,0xbd2cbdf1,0x3d84bddc,0x3cc83dfb,0xbd713de2,0xbbc93e00,0xbdce3d98,
0x3d803d80,0x3d713de2,0x3ddc3d84,0xbbc93e00,0xbcc83dfb,0x3da2bdc6,0x3c96bdfd,0x3df1bd2c,0x3dfbbcc8,0xbdf5bd15,0xbdf83cf9,0xbdacbdbe,0xbd8ebdd5,0x3c493dff,0x3d983dce,0xbd5b3de7,
0xbd803d80,0xbd15bdf5,0xbdcebd98,0x3d2cbdf1,0xbdfb3cc8,0xbdffbc49,0xbddc3d84,0xbdbebdac,0xbcc83dfb,0xbd713de2,0x3c963dfd,0xbde73d5b,0x3dd53d8e,0x3da23dc6,0x3df83cf9,0x3bc93e00,
0x3d803d80,0x3c493dff,0x3dbe3dac,0xbd983dce,0xbd8ebdd5,0x3d713de2,0x3df13d2c,0xbcf93df8,0xbdd5bd8e,0x3dc63da2,0x3e00bbc9,0x3c963dfd,0xbdfbbcc8,0x3df53d15,0x3de7bd5b,0x3d843ddc,
0xbd803d80,0x3c49bdff,0xbdacbdbe,0x3dcebd98,0x3d8ebdd5,0x3d71bde2,0xbd2cbdf1,0x3df8bcf9,0x3dd5bd8e,0x3dc6bda2,0x3bc9be00,0x3dfd3c96,0x3dfbbcc8,0x3df5bd15,0x3d5bbde7,0x3ddc3d84,
0x3d803d80,0xbd153df5,0x3d983dce,0xbdf13d2c,0x3dfb3cc8,0xbdff3c49,0xbd843ddc,0xbdacbdbe,0x3cc83dfb,0xbd71bde2,0xbdfdbc96,0x3d5bbde7,0xbdd53d8e,0x3da2bdc6,0xbcf9bdf8,0x3e003bc9,
0xbd803d80,0x3d71bde2,0xbd84bddc,0x3e00bbc9,0x3cc83dfb,0x3da23dc6,0x3dfdbc96,0xbd2c3df1,0xbdfbbcc8,0xbdf53d15,0xbcf93df8,0xbdbebdac,0x3d8ebdd5,0x3c49bdff,0xbdcebd98,0x3de7bd5b,
0x3d803d80,0xbda23dc6,0x3d5b3de7,0xbdf8bcf9,0xbdd53d8e,0x3d15bdf5,0xbdbebdac,0x3dfdbc96,0x3d8ebdd5,0x3c493dff,0x3df13d2c,0xbddc3d84,0xbcc83dfb,0xbd71bde2,0xbe003bc9,0x3d98bdce,
0xbd803d80,0x3dc6bda2,0xbd2cbdf1,0x3ddc3d84,0xbdd5bd8e,0xbdf53d15,0xbbc93e00,0xbd98bdce,0x3d8e3dd5,0x3dff3c49,0x3d5bbde7,0x3cf93df8,0xbcc8bdfb,0xbde2bd71,0xbdbe3dac,0x3c96bdfd,
0x3d803d80,0xbde23d71,0x3cf93df8,0xbdacbdbe,0x3cc8bdfb,0x3dc63da2,0x3dcebd98,0xbd5b3de7,0xbdfb3cc8,0x3d15bdf5,0xbddcbd84,0x3e003bc9,0x3d8e3dd5,0xbdff3c49,0xbc963dfd,0xbd2cbdf1,
0xbd803d80,0x3df5bd15,0xbc96bdfd,0x3d5b3de7,0x3dfbbcc8,0x3c49bdff,0xbdf8bcf9,0x3e00bbc9,0x3cc8bdfb,0xbde2bd71,0xbd983dce,0x3d2cbdf1,0xbdd5bd8e,0xbdc63da2,0x3d843ddc,0xbdbebdac,
0x3d803d80,0xbdff3c49,0x3bc93e00,0xbc96bdfd,0x3d8e3dd5,0xbde23d71,0x3d5b3de7,0xbd84bddc,0x3dd53d8e,0xbda23dc6,0x3dbe3dac,0xbdcebd98,0x3dfb3cc8,0xbd153df5,0x3df13d2c,0xbdf8bcf9,
0xbd803d80,0x3dff3c49,0x3bc9be00,0xbc963dfd,0xbd8e3dd5,0x3de23d71,0x3d5bbde7,0xbd843ddc,0xbdd53d8e,0x3da23dc6,0x3dbebdac,0xbdce3d98,0xbdfb3cc8,0x3d153df5,0x3df1bd2c,0xbdf83cf9,
0x3d803d80,0xbdf5bd15,0xbc963dfd,0x3d5bbde7,0xbdfbbcc8,0xbc49bdff,0xbdf83cf9,0x3e003bc9,0xbcc8bdfb,0x3de2bd71,0xbd98bdce,0x3d2c3df1,0x3dd5bd8e,0x3dc63da2,0x3d84bddc,0xbdbe3dac,
0xbd803d80,0x3de23d71,0x3cf9bdf8,0xbdac3dbe,0xbcc8bdfb,0xbdc63da2,0x3dce3d98,0xbd5bbde7,0x3dfb3cc8,0xbd15bdf5,0xbddc3d84,0x3e00bbc9,0xbd8e3dd5,0x3dff3c49,0xbc96bdfd,0xbd2c3df1,
0x3d803d80,0xbdc6bda2,0xbd2c3df1,0x3ddcbd84,0x3dd5bd8e,0x3df53d15,0xbbc9be00,0xbd983dce,0xbd8e3dd5,0xbdff3c49,0x3d5b3de7,0x3cf9bdf8,0x3cc8bdfb,0x3de2bd71,0xbdbebdac,0x3c963dfd,
0xbd803d80,0x3da23dc6,0x3d5bbde7,0xbdf83cf9,0x3dd53d8e,0xbd15bdf5,0xbdbe3dac,0x3dfd3c96,0xbd8ebdd5,0xbc493dff,0x3df1bd2c,0xbddcbd84,0x3cc83dfb,0x3d71bde2,0xbe00bbc9,0x3d983dce,
0x3d803d80,0xbd71bde2,0xbd843ddc,0x3e003bc9,0xbcc83dfb,0xbda23dc6,0x3dfd3c96,0xbd2cbdf1,0x3dfbbcc8,0x3df53d15,0xbcf9bdf8,0xbdbe3dac,0xbd8ebdd5,0xbc49bdff,0xbdce3d98,0x3de73d5b,
0xbd803d80,0x3d153df5,0x3d98bdce,0xbdf1bd2c,0xbdfb3cc8,0x3dff3c49,0xbd84bddc,0xbdac3dbe,0xbcc83dfb,0x3d71bde2,0xbdfd3c96,0x3d5b3de7,0x3dd53d8e,0xbda2bdc6,0xbcf93df8,0x3e00bbc9,
0x3d803d80,0xbc49bdff,0xbdac3dbe,0x3dce3d98,0xbd8ebdd5,0xbd71bde2,0xbd2c3df1,0x3df83cf9,0xbdd5bd8e,0xbdc6bda2,0x3bc93e00,0x3dfdbc96,0xbdfbbcc8,0xbdf5bd15,0x3d5b3de7,0x3ddcbd84,
0xbd803d80,0xbc493dff,0x3dbebdac,0xbd98bdce,0x3d8ebdd5,0xbd713de2,0x3df1bd2c,0xbcf9bdf8,0x3dd5bd8e,0xbdc63da2,0x3e003bc9,0x3c96bdfd,0x3dfbbcc8,0xbdf53d15,0x3de73d5b,0x3d84bddc,
0x3d803d80,0x3d15bdf5,0xbdce3d98,0x3d2c3df1,0x3dfb3cc8,0x3dffbc49,0xbddcbd84,0xbdbe3dac,0x3cc83dfb,0x3d713de2,0x3c96bdfd,0xbde7bd5b,0xbdd53d8e,0xbda23dc6,0x3df8bcf9,0x3bc9be00,
0xbd803d80,0xbd713de2,0x3ddcbd84,0xbbc9be00,0x3cc83dfb,0xbda2bdc6,0x3c963dfd,0x3df13d2c,0xbdfbbcc8,0x3df5bd15,0xbdf8bcf9,0xbdac3dbe,0x3d8ebdd5,0xbc493dff,0x3d98bdce,0xbd5bbde7,
0x3d803d80,0x3da2bdc6,0xbde73d5b,0xbcf93df8,0xbdd53d8e,0xbd153df5,0x3dacbdbe,0xbc96bdfd,0x3d8ebdd5,0xbc49bdff,0xbd2c3df1,0x3d843ddc,0xbcc83dfb,0x3d713de2,0xbbc9be00,0xbdcebd98,
0xbd803d80,0xbdc63da2,0x3df1bd2c,0x3d84bddc,0xbdd5bd8e,0x3df5bd15,0xbe00bbc9,0xbdce3d98,0x3d8e3dd5,0xbdffbc49,0x3de73d5b,0x3df8bcf9,0xbcc8bdfb,0x3de23d71,0xbdacbdbe,0xbdfdbc96,
0x3d803d80,0x3de2bd71,0xbdf83cf9,0xbdbe3dac,0x3cc8bdfb,0xbdc6bda2,0x3d983dce,0x3de73d5b,0xbdfb3cc8,0xbd153df5,0x3d84bddc,0x3bc9be00,0x3d8e3dd5,0x3dffbc49,0xbdfdbc96,0xbdf13d2c,
0xbd803d80,0xbdf53d15,0x3dfdbc96,0x3de7bd5b,0x3dfbbcc8,0xbc493dff,0x3cf9bdf8,0xbbc9be00,0x3cc8bdfb,0x3de23d71,0xbdcebd98,0xbdf1bd2c,0xbdd5bd8e,0x3dc6bda2,0xbddc3d84,0xbdac3dbe,
0x3d803d80,0x3dffbc49,0xbe003bc9,0xbdfd3c96,0x3d8e3dd5,0x3de2bd71,0xbde73d5b,0xbddc3d84,0x3dd53d8e,0x3da2bdc6,0xbdac3dbe,0xbd983dce,0x3dfb3cc8,0x3d15bdf5,0xbd2c3df1,0xbcf93df8,
0xbd153df5,0xbc963dfd,0xbc173dff,0xbce03dfa,0xbd8e3dd5,0xbdac3dbe,0xbd9d3dca,0xbdb93db1,0xbded3d44,0xbdf83cf9,0xbdf33d21,0xbdfc3caf,0xbdfbbcc8,0xbdf1bd2c,0xbdf7bd09,0xbdeabd4f,
0xbda23dc6,0xbd2c3df1,0xbcaf3dfc,0xbd7c3ddf,0xbdfb3cc8,0xbdfdbc96,0xbe003b49,0xbdf3bd21,0xbd44bded,0xbbc9be00,0xbce0bdfa,0x3c7bbdfe,0x3dd5bd8e,0x3df8bcf9,0x3deabd4f,0x3dffbc17,
0xbde23d71,0xbd843ddc,0xbd093df7,0xbdb93db1,0xbdd5bd8e,0xbd5bbde7,0xbda7bdc2,0xbcafbdfc,0x3dedbd44,0x3dfd3c96,0x3dfebc7b,0x3dea3d4f,0xbcc83dfb,0xbdac3dbe,0xbd663de5,0xbdd83d89,
0xbdff3c49,0xbdac3dbe,0xbd383def,0xbde53d66,0xbcc8bdfb,0x3d84bddc,0x3cafbdfc,0x3dcabd9d,0x3d443ded,0xbd2c3df1,0x3b493e00,0xbda73dc2,0xbd8ebdd5,0x3c96bdfd,0xbce0bdfa,0x3d7cbddf,
0xbdf5bd15,0xbdce3d98,0xbd663de5,0xbdfc3caf,0x3d8ebdd5,0x3e00bbc9,0x3ddfbd7c,0x3dea3d4f,0xbded3d44,0xbddcbd84,0xbdffbc17,0xbd89bdd8,0x3dfb3cc8,0x3d5b3de7,0x3dca3d9d,0xbb493e00,
0xbdc6bda2,0xbde73d5b,0xbd893dd8,0xbdfebc7b,0x3dfbbcc8,0x3d983dce,0x3def3d38,0x3c173dff,0xbd44bded,0x3dacbdbe,0x3cafbdfc,0x3df7bd09,0xbdd53d8e,0xbddcbd84,0xbe003b49,0xbd66bde5,
0xbd71bde2,0xbdf83cf9,0xbd9d3dca,0xbdeabd4f,0x3dd53d8e,0xbd2c3df1,0x3d213df3,0xbdd83d89,0x3dedbd44,0x3d983dce,0x3df73d09,0xbb493e00,0x3cc8bdfb,0x3e00bbc9,0x3dc2bda7,0x3dd13d93,
0xbc49bdff,0xbe003bc9,0xbdb13db9,0xbdc2bda7,0x3cc83dfb,0xbdf83cf9,0xbd893dd8,0xbddfbd7c,0x3d443ded,0xbde73d5b,0xbd383def,0xbdf3bd21,0x3d8e3dd5,0xbdce3d98,0xbcaf3dfc,0xbdfebc7b,
0x3d15bdf5,0xbdfdbc96,0xbdc23da7,0xbd89bdd8,0xbd8e3dd5,0xbdbebdac,0xbdfe3c7b,0x3b49be00,0xbded3d44,0xbcf9bdf8,0xbde5bd66,0x3d93bdd1,0xbdfbbcc8,0x3d2cbdf1,0xbd7cbddf,0x3defbd38,
0x3da2bdc6,0xbdf1bd2c,0xbdd13d93,0xbd09bdf7,0xbdfb3cc8,0x3c96bdfd,0xbdb9bdb1,0x3de5bd66,0xbd44bded,0x3e00bbc9,0x3d89bdd8,0x3d9d3dca,0x3dd5bd8e,0x3cf93df8,0x3def3d38,0xbda73dc2,
0x3de2bd71,0xbddcbd84,0xbddf3d7c,0x3b49be00,0xbdd5bd8e,0x3de7bd5b,0x3c17bdff,0x3dd13d93,0x3dedbd44,0xbc963dfd,0x3dca3d9d,0xbdef3d38,0xbcc83dfb,0xbdbebdac,0xbdf33d21,0x3ce0bdfa,
0x3dffbc49,0xbdbebdac,0xbdea3d4f,0x3d21bdf3,0xbcc8bdfb,0x3ddc3d84,0x3dd1bd93,0xbc7b3dfe,0x3d443ded,0xbdf1bd2c,0xbdb13db9,0xbc17bdff,0xbd8ebdd5,0x3dfd3c96,0x3d89bdd8,0x3d093df7,
0x3df53d15,0xbd98bdce,0xbdf33d21,0x3d93bdd1,0x3d8ebdd5,0x3bc93e00,0x3df73d09,0xbdef3d38,0xbded3d44,0x3d84bddc,0xbda7bdc2,0x3dfa3ce0,0x3dfb3cc8,0xbde73d5b,0x3c7b3dfe,0xbdb1bdb9,
0x3dc63da2,0xbd5bbde7,0xbdfa3ce0,0x3dcabd9d,0x3dfbbcc8,0xbdce3d98,0x3d4f3dea,0xbdc2bda7,0xbd44bded,0x3dbe3dac,0x3dd1bd93,0xbd7c3ddf,0xbdd53d8e,0x3d84bddc,0xbdb9bdb1,0x3df33d21,
0x3d713de2,0xbcf9bdf8,0xbdfe3c7b,0x3defbd38,0x3dd53d8e,0xbdf1bd2c,0xbd663de5,0x3ce0bdfa,0x3dedbd44,0xbdce3d98,0x3d7c3ddf,0xbdb1bdb9,0x3cc8bdfb,0x3bc93e00,0x3dff3c17,0xbdfc3caf,
0x3c493dff,0xbbc9be00,0xbe003b49,0x3dffbc17,0x3cc83dfb,0xbcf9bdf8,0xbdfa3ce0,0x3df7bd09,0x3d443ded,0xbd5bbde7,0xbdea3d4f,0x3de5bd66,0x3d8e3dd5,0xbd98bdce,0xbdd13d93,0x3dcabd9d,
0xbd153df5,0x3c96bdfd,0xbdffbc17,0x3dfa3ce0,0xbd8e3dd5,0x3dacbdbe,0xbdcabd9d,0x3db13db9,0xbded3d44,0x3df8bcf9,0xbd21bdf3,0x3caf3dfc,0xbdfbbcc8,0x3df13d2c,0x3d09bdf7,0xbd4f3dea,
0xbda23dc6,0x3d2cbdf1,0xbdfcbcaf,0x3ddf3d7c,0xbdfb3cc8,0x3dfd3c96,0xbb49be00,0xbd213df3,0xbd44bded,0x3bc93e00,0x3dfabce0,0xbdfebc7b,0x3dd5bd8e,0xbdf83cf9,0x3d4f3dea,0xbc17bdff,
0xbde23d71,0x3d84bddc,0xbdf7bd09,0x3db13db9,0xbdd5bd8e,0x3d5b3de7,0x3dc2bda7,0xbdfc3caf,0x3dedbd44,0xbdfdbc96,0x3c7b3dfe,0x3d4fbdea,0xbcc83dfb,0x3dacbdbe,0xbde5bd66,0x3d893dd8,
0xbdff3c49,0x3dacbdbe,0xbdefbd38,0x3d663de5,0xbcc8bdfb,0xbd843ddc,0x3dfc3caf,0xbd9dbdca,0x3d443ded,0x3d2cbdf1,0xbe003b49,0x3dc23da7,0xbd8ebdd5,0xbc963dfd,0x3dfabce0,0xbddfbd7c,
0xbdf5bd15,0x3dcebd98,0xbde5bd66,0x3caf3dfc,0x3d8ebdd5,0xbe003bc9,0x3d7c3ddf,0x3d4fbdea,0xbded3d44,0x3ddc3d84,0x3c17bdff,0xbdd83d89,0x3dfb3cc8,0xbd5bbde7,0xbd9d3dca,0x3e003b49,
0xbdc6bda2,0x3de7bd5b,0xbdd8bd89,0xbc7b3dfe,0x3dfbbcc8,0xbd98bdce,0xbd383def,0x3dffbc17,0xbd44bded,0xbdac3dbe,0x3dfc3caf,0xbd09bdf7,0xbdd53d8e,0x3ddc3d84,0xbb49be00,0xbde53d66,
0xbd71bde2,0x3df8bcf9,0xbdcabd9d,0xbd4f3dea,0x3dd53d8e,0x3d2cbdf1,0xbdf33d21,0x3d893dd8,0x3dedbd44,0xbd98bdce,0xbd093df7,0x3e003b49,0x3cc8bdfb,0xbe003bc9,0x3da73dc2,0x3d93bdd1,
0xbc49bdff,0x3e00bbc9,0xbdb9bdb1,0xbda73dc2,0x3cc83dfb,0x3df8bcf9,0xbdd8bd89,0xbd7c3ddf,0x3d443ded,0x3de7bd5b,0xbdefbd38,0xbd213df3,0x3d8e3dd5,0x3dcebd98,0xbdfcbcaf,0xbc7b3dfe,
0x3d15bdf5,0x3dfd3c96,0xbda7bdc2,0xbdd83d89,0xbd8e3dd5,0x3dbe3dac,0xbc7bbdfe,0xbe00bb49,0xbded3d44,0x3cf93df8,0x3d66bde5,0xbdd1bd93,0xbdfbbcc8,0xbd2c3df1,0x3ddfbd7c,0xbd38bdef,
0x3da2bdc6,0x3df13d2c,0xbd93bdd1,0xbdf73d09,0xbdfb3cc8,0xbc963dfd,0x3db1bdb9,0xbd66bde5,0xbd44bded,0xbe003bc9,0x3dd83d89,0x3dcabd9d,0x3dd5bd8e,0xbcf9bdf8,0xbd383def,0x3dc23da7,
0x3de2bd71,0x3ddc3d84,0xbd7cbddf,0xbe00bb49,0xbdd5bd8e,0xbde73d5b,0x3dff3c17,0x3d93bdd1,0x3dedbd44,0x3c96bdfd,0xbd9d3dca,0x3d383def,0xbcc83dfb,0x3dbe3dac,0xbd21bdf3,0xbdfabce0,
0x3dffbc49,0x3dbe3dac,0xbd4fbdea,0xbdf3bd21,0xbcc8bdfb,0xbddcbd84,0x3d933dd1,0x3dfe3c7b,0x3d443ded,0x3df13d2c,0xbdb9bdb1,0xbdff3c17,0xbd8ebdd5,0xbdfdbc96,0x3dd83d89,0x3df7bd09,
0x3df53d15,0x3d983dce,0xbd21bdf3,0xbdd1bd93,0x3d8ebdd5,0xbbc9be00,0xbd093df7,0x3d383def,0xbded3d44,0xbd843ddc,0x3dc2bda7,0x3ce0bdfa,0x3dfb3cc8,0x3de7bd5b,0xbdfe3c7b,0xbdb93db1,
0x3dc63da2,0x3d5b3de7,0xbce0bdfa,0xbd9dbdca,0x3dfbbcc8,0x3dcebd98,0xbdea3d4f,0xbda73dc2,0xbd44bded,0xbdbebdac,0x3d933dd1,0x3ddf3d7c,0xbdd53d8e,0xbd843ddc,0x3db1bdb9,0x3d21bdf3,
0x3d713de2,0x3cf93df8,0xbc7bbdfe,0xbd38bdef,0x3dd53d8e,0x3df13d2c,0xbde5bd66,0xbdfabce0,0x3dedbd44,0x3dcebd98,0xbddf3d7c,0xbdb93db1,0x3cc8bdfb,0xbbc9be00,0xbc173dff,0x3caf3dfc,
0x3c493dff,0x3bc93e00,0xbb49be00,0xbc17bdff,0x3cc83dfb,0x3cf93df8,0xbce0bdfa,0xbd09bdf7,0x3d443ded,0x3d5b3de7,0xbd4fbdea,0xbd66bde5,0x3d8e3dd5,0x3d983dce,0xbd93bdd1,0xbd9dbdca,
0xbdb53d80,0xbd98bdce,0xbda7bdc2,0xbd89bdd8,0xbdc63da2,0xbbc9be00,0xbc7bbdfe,0x3b49be00,0xbdff3c49,0x3d84bddc,0x3d66bde5,0x3d93bdd1,0xbde2bd71,0x3de7bd5b,0x3ddfbd7c,0x3defbd38,
0x3db53d80,0x3d5b3de7,0x3d933dd1,0x3d093df7,0xbde2bd71,0xbdce3d98,0xbdb13db9,0xbde53d66,0x3d15bdf5,0xbdbebdac,0xbdd8bd89,0xbd9dbdca,0x3dff3c49,0x3d84bddc,0x3d38bdef,0x3da7bdc2,
0xbdb53d80,0xbcf9bdf8,0xbd7cbddf,0x3b49be00,0x3c49bdff,0x3df13d2c,0x3dff3c17,0x3dd13d93,0x3dc63da2,0xbdce3d98,0xbd9d3dca,0xbdef3d38,0xbdf53d15,0xbbc9be00,0xbd21bdf3,0x3ce0bdfa,
0x3db53d80,0x3bc93e00,0x3d4f3dea,0xbd213df3,0x3df5bd15,0xbcf9bdf8,0xbd93bdd1,0x3c7bbdfe,0xbde23d71,0x3d5b3de7,0x3db93db1,0x3c173dff,0x3dc6bda2,0xbd98bdce,0xbdd8bd89,0xbd09bdf7,
0xbdb53d80,0x3c96bdfd,0xbd21bdf3,0x3d93bdd1,0x3da23dc6,0xbdac3dbe,0xbd093df7,0xbdef3d38,0xbc49bdff,0x3df8bcf9,0x3dc2bda7,0x3dfa3ce0,0xbd713de2,0xbdf1bd2c,0xbdfe3c7b,0xbdb1bdb9,
0x3db53d80,0xbd2c3df1,0x3ce03dfa,0xbdca3d9d,0xbd713de2,0x3dfd3c96,0x3deabd4f,0x3dc23da7,0x3df53d15,0xbbc9be00,0xbd93bdd1,0x3d7cbddf,0x3c49bdff,0xbdf83cf9,0xbdb13db9,0xbdf3bd21,
0xbdb53d80,0x3d84bddc,0xbc7bbdfe,0x3defbd38,0xbdffbc49,0xbd5bbde7,0xbde5bd66,0x3ce0bdfa,0xbda23dc6,0xbdfdbc96,0xbddf3d7c,0xbdb1bdb9,0x3d153df5,0xbdac3dbe,0xbc173dff,0xbdfc3caf,
0x3db53d80,0xbdac3dbe,0x3b493e00,0xbdff3c17,0xbd15bdf5,0xbd843ddc,0x3ce03dfa,0xbdf73d09,0xbd71bde2,0xbd2c3df1,0x3d4f3dea,0xbde53d66,0xbda2bdc6,0xbc963dfd,0x3d933dd1,0xbdca3d9d,
0xbdb53d80,0x3dcebd98,0x3c17bdff,0x3dfa3ce0,0x3dc6bda2,0x3e00bbc9,0x3d9dbdca,0x3db13db9,0x3dffbc49,0x3ddc3d84,0x3df3bd21,0x3caf3dfc,0x3de23d71,0x3d5b3de7,0x3df73d09,0xbd4f3dea,
0x3db53d80,0xbde73d5b,0xbcaf3dfc,0xbddfbd7c,0x3de23d71,0xbd98bdce,0xbe003b49,0x3d21bdf3,0xbd153df5,0x3dacbdbe,0xbce0bdfa,0x3dfe3c7b,0xbdffbc49,0x3ddc3d84,0x3deabd4f,0x3c173dff,
0xbdb53d80,0x3df8bcf9,0x3d09bdf7,0x3db13db9,0xbc493dff,0xbd2c3df1,0x3da73dc2,0xbdfc3caf,0xbdc6bda2,0xbd98bdce,0xbdfe3c7b,0x3d4fbdea,0x3df5bd15,0x3e00bbc9,0x3d66bde5,0x3d893dd8,
0x3db53d80,0xbe003bc9,0xbd383def,0xbd66bde5,0xbdf53d15,0x3df8bcf9,0x3cafbdfc,0x3d9d3dca,0x3de2bd71,0xbde73d5b,0x3b493e00,0xbdc2bda7,0xbdc63da2,0x3dcebd98,0xbce0bdfa,0x3ddf3d7c,
0xbdb53d80,0x3dfd3c96,0x3d66bde5,0x3caf3dfc,0xbda2bdc6,0xbdbebdac,0xbddf3d7c,0x3d4fbdea,0x3c493dff,0x3cf93df8,0x3dff3c17,0xbdd83d89,0x3d71bde2,0x3d2cbdf1,0xbdcabd9d,0x3e003b49,
0x3db53d80,0xbdf1bd2c,0xbd893dd8,0x3c7bbdfe,0x3d71bde2,0xbc963dfd,0x3def3d38,0xbdff3c17,0xbdf5bd15,0x3e00bbc9,0x3cafbdfc,0x3d093df7,0xbc493dff,0xbcf9bdf8,0xbe003b49,0x3de5bd66,
0xbdb53d80,0x3ddc3d84,0x3d9dbdca,0xbd4f3dea,0x3dff3c49,0x3de7bd5b,0xbd21bdf3,0x3d893dd8,0x3da2bdc6,0x3c96bdfd,0xbdf7bd09,0x3e003b49,0xbd15bdf5,0xbdbebdac,0xbdc23da7,0x3d93bdd1,
0x3db53d80,0xbdbebdac,0xbdb13db9,0x3da7bdc2,0x3d153df5,0xbddcbd84,0xbd893dd8,0x3d7cbddf,0x3d713de2,0xbdf1bd2c,0xbd383def,0x3d21bdf3,0x3da23dc6,0xbdfdbc96,0xbcaf3dfc,0x3c7bbdfe,
0xbdb53d80,0x3d983dce,0x3dc2bda7,0xbdd83d89,0xbdc63da2,0x3bc93e00,0x3dfebc7b,0xbe00bb49,0xbdff3c49,0xbd843ddc,0x3de53d66,0xbdd1bd93,0xbde2bd71,0xbde73d5b,0x3d7c3ddf,0xbd38bdef,
0x3db53d80,0xbd5bbde7,0xbdd13d93,0x3df7bd09,0xbde2bd71,0x3dcebd98,0xbdb9bdb1,0x3d663de5,0x3d15bdf5,0x3dbe3dac,0x3d89bdd8,0xbdca3d9d,0x3dff3c49,0xbd843ddc,0x3def3d38,0xbdc2bda7,
0xbdb53d80,0x3cf93df8,0x3ddfbd7c,0xbe00bb49,0x3c49bdff,0xbdf1bd2c,0xbc173dff,0x3d93bdd1,0x3dc63da2,0x3dcebd98,0xbdcabd9d,0x3d383def,0xbdf53d15,0x3bc93e00,0x3df3bd21,0xbdfabce0,
0x3db53d80,0xbbc9be00,0xbdea3d4f,0x3df33d21,0x3df5bd15,0x3cf93df8,0x3dd1bd93,0xbdfebc7b,0xbde23d71,0xbd5bbde7,0xbdb13db9,0x3dffbc17,0x3dc6bda2,0x3d983dce,0x3d89bdd8,0xbdf73d09,
0xbdb53d80,0xbc963dfd,0x3df3bd21,0xbdd1bd93,0x3da23dc6,0x3dacbdbe,0xbdf7bd09,0x3d383def,0xbc49bdff,0xbdf83cf9,0x3da73dc2,0x3ce0bdfa,0xbd713de2,0x3df13d2c,0xbc7bbdfe,0xbdb93db1,
0x3db53d80,0x3d2cbdf1,0xbdfa3ce0,0x3d9d3dca,0xbd713de2,0xbdfdbc96,0x3d4f3dea,0x3da7bdc2,0x3df53d15,0x3bc93e00,0x3dd1bd93,0xbddfbd7c,0x3c49bdff,0x3df8bcf9,0xbdb9bdb1,0xbd213df3,
0xbdb53d80,0xbd843ddc,0x3dfebc7b,0xbd38bdef,0xbdffbc49,0x3d5b3de7,0x3d66bde5,0xbdfabce0,0xbda23dc6,0x3dfd3c96,0xbd7cbddf,0xbdb93db1,0x3d153df5,0x3dacbdbe,0xbdffbc17,0x3caf3dfc,
0x3db53d80,0x3dacbdbe,0xbe003b49,0x3c173dff,0xbd15bdf5,0x3d84bddc,0xbdfa3ce0,0x3d093df7,0xbd71bde2,0x3d2cbdf1,0xbdea3d4f,0x3d663de5,0xbda2bdc6,0x3c96bdfd,0xbdd13d93,0x3d9d3dca,
0xbdb53d80,0xbdce3d98,0x3dff3c17,0x3ce0bdfa,0x3dc6bda2,0xbe003bc9,0x3dca3d9d,0x3db9bdb1,0x3dffbc49,0xbddcbd84,0x3d213df3,0x3dfcbcaf,0x3de23d71,0xbd5bbde7,0xbd093df7,0x3dea3d4f,
0x3db53d80,0x3de7bd5b,0xbdfcbcaf,0xbd7c3ddf,0x3de23d71,0x3d983dce,0xbb49be00,0xbdf3bd21,0xbd153df5,0xbdac3dbe,0x3dfabce0,0x3c7bbdfe,0xbdffbc49,0xbddcbd84,0x3d4f3dea,0x3dffbc17,
0xbdb53d80,0xbdf83cf9,0x3df73d09,0x3db9bdb1,0xbc493dff,0x3d2cbdf1,0xbdc23da7,0x3caf3dfc,0xbdc6bda2,0x3d983dce,0xbc7bbdfe,0xbdeabd4f,0x3df5bd15,0xbe003bc9,0x3de53d66,0x3dd8bd89,
0x3db53d80,0x3e00bbc9,0xbdefbd38,0xbde53d66,0xbdf53d15,0xbdf83cf9,0x3dfc3caf,0x3dcabd9d,0x3de2bd71,0x3de7bd5b,0xbe003b49,0xbda73dc2,0xbdc63da2,0xbdce3d98,0x3dfabce0,0x3d7cbddf,
0xbdb53d80,0xbdfdbc96,0x3de53d66,0x3dfcbcaf,0xbda2bdc6,0x3dbe3dac,0xbd7cbddf,0xbdeabd4f,0x3c493dff,0xbcf9bdf8,0xbc173dff,0x3d893dd8,0x3d71bde2,0xbd2c3df1,0x3d9dbdca,0x3b49be00,
0x3db53d80,0x3df13d2c,0xbdd8bd89,0xbdfebc7b,0x3d71bde2,0x3c96bdfd,0xbd383def,0x3c173dff,0xbdf5bd15,0xbe003bc9,0x3dfc3caf,0x3df7bd09,0xbc493dff,0x3cf93df8,0xbb49be00,0xbd66bde5,
0xbdb53d80,0xbddcbd84,0x3dca3d9d,0x3dea3d4f,0x3dff3c49,0xbde73d5b,0x3df3bd21,0x3dd8bd89,0x3da2bdc6,0xbc963dfd,0x3d09bdf7,0x3b49be00,0xbd15bdf5,0x3dbe3dac,0xbda7bdc2,0xbdd1bd93,
0x3db53d80,0x3dbe3dac,0xbdb9bdb1,0xbdc2bda7,0x3d153df5,0x3ddc3d84,0xbdd8bd89,0xbddfbd7c,0x3d713de2,0x3df13d2c,0xbdefbd38,0xbdf3bd21,0x3da23dc6,0x3dfd3c96,0xbdfcbcaf,0xbdfebc7b,
0x3f800000,0x0,0x3f800000,0x0,0x3f800000,0x0,0x3f800000,0x0,0x3f800000,0x0,0x3f800000,0x0,0x3f800000,0x0,0x3f800000,0x0,
0x3f800000,0x0,0x3f7ffb11,0xbc490e90,0x3f7fec43,0xbcc90ab0,0x3f7fd397,0xbd16c32c,0x3f7fb10f,0xbd48fb30,0x3f7f84ab,0xbd7b2b74,0x3f7f4e6d,0xbd96a905,0x3f7f0e58,0xbdafb680,
0x3f800000,0x0,0x3f7fec43,0xbcc90ab0,0x3f7fb10f,0xbd48fb30,0x3f7f4e6d,0xbd96a905,0x3f7ec46d,0xbdc8bd36,0x3f7e1324,0xbdfab273,0x3f7d3aac,0xbe164083,0x3f7c3b28,0xbe2f10a2,
0x3f800000,0x0,0x3f7fd397,0xbd16c32c,0x3f7f4e6d,0xbd96a905,0x3f7e70b0,0xbde1bc2e,0x3f7d3aac,0xbe164083,0x3f7baccd,0xbe3b6ecf,0x3f79c79d,0xbe605c13,0x3f778bc5,0xbe827dc0,
0x3f800000,0x0,0x3f7fb10f,0xbd48fb30,0x3f7ec46d,0xbdc8bd36,0x3f7d3aac,0xbe164083,0x3f7b14be,0xbe47c5c2,0x3f7853f8,0xbe78cfcc,0x3f74fa0b,0xbe94a031,0x3f710908,0xbeac7cd4,
0x3f800000,0x0,0x3f7f84ab,0xbd7b2b74,0x3f7e1324,0xbdfab273,0x3f7baccd,0xbe3b6ecf,0x3f7853f8,0xbe78cfcc,0x3f740bdd,0xbe9aa086,0x3f6ed89e,0xbeb8442a,0x3f68bf3c,0xbed53641,
0x3f800000,0x0,0x3f7f4e6d,0xbd96a905,0x3f7d3aac,0xbe164083,0x3f79c79d,0xbe605c13,0x3f74fa0b,0xbe94a031,0x3f6ed89e,0xbeb8442a,0x3f676bd8,0xbedae880,0x3f5ebe05,0xbefc5d27,
0x3f800000,0x0,0x3f7f0e58,0xbdafb680,0x3f7c3b28,0xbe2f10a2,0x3f778bc5,0xbe827dc0,0x3f710908,0xbeac7cd4,0x3f68bf3c,0xbed53641,0x3f5ebe05,0xbefc5d27,0x3f531849,0xbf10d3cd,
0x3f800000,0x0,0x3f7b14be,0xbe47c5c2,0x3f6c835e,0xbec3ef15,0x3f54db31,0xbf0e39da,0x3f3504f3,0xbf3504f3,0x3f0e39da,0xbf54db31,0x3ec3ef15,0xbf6c835e,0x3e47c5c2,0xbf7b14be,
0x3f800000,0x0,0x3f7a7302,0xbe541501,0x3f6a09a7,0xbecf7bca,0x3f4f7a1f,0xbf15f6d9,0x3f2beb4a,0xbf3daef9,0x3f00e7e4,0xbf5d2d53,0x3ea09ae5,0xbf731447,0x3de1bc2e,0xbf7e70b0,
0x3f800000,0x0,0x3f79c79d,0xbe605c13,0x3f676bd8,0xbedae880,0x3f49d112,0xbf1d7fd1,0x3f226799,0xbf45e403,0x3ee63375,0xbf64aa59,0x3e78cfcc,0xbf7853f8,0x3cc90ab0,0xbf7fec43,
0x3f800000,0x0,0x3f791298,0xbe6c9a7f,0x3f64aa59,0xbee63375,0x3f43e200,0xbf24d225,0x3f187fc0,0xbf4d9f02,0x3ec9b953,0xbf6b4b0c,0x3e2f10a2,0xbf7c3b28,0xbd7b2b74,0xbf7f84ab,
0x3f800000,0x0,0x3f7853f8,0xbe78cfcc,0x3f61c598,0xbef15aea,0x3f3daef9,0xbf2beb4a,0x3f0e39da,0xbf54db31,0x3eac7cd4,0xbf710908,0x3dc8bd36,0xbf7ec46d,0xbe164083,0xbf7d3aac,
0x3f800000,0x0,0x3f778bc5,0xbe827dc0,0x3f5ebe05,0xbefc5d27,0x3f373a23,0xbf32c8c9,0x3f039c3d,0xbf5b941a,0x3e8e9a22,0xbf75dec6,0x3cc90ab0,0xbf7fec43,0xbe6c9a7f,0xbf791298,
0x3f800000,0x0,0x3f76ba07,0xbe888e93,0x3f5b941a,0xbf039c3d,0x3f3085bb,0xbf396842,0x3ef15aea,0xbf61c598,0x3e605c13,0xbf79c79d,0xbd48fb30,0xbf7fb10f,0xbea09ae5,0xbf731447,
0x3f800000,0x0,0x3f75dec6,0xbe8e9a22,0x3f584853,0xbf08f59b,0x3f299415,0xbf3fc767,0x3edae880,0xbf676bd8,0x3e22abb6,0xbf7cbfc9,0xbdfab273,0xbf7e1324,0xbec9b953,0xbf6b4b0c,
0x3f800000,0x0,0x3f7ec46d,0xbdc8bd36,0x3f7b14be,0xbe47c5c2,0x3f74fa0b,0xbe94a031,0x3f6c835e,0xbec3ef15,0x3f61c598,0xbef15aea,0x3f54db31,0xbf0e39da,0x3f45e403,0xbf226799,
0x3f800000,0x0,0x3f6b4b0c,0xbec9b953,0x3f3085bb,0xbf396842,0x3eb263ef,0xbf6ff573,0xbd48fb30,0xbf7fb10f,0xbee0924f,0xbf660f88,0xbf41d870,0xbf273656,0xbf740bdd,0xbe9aa086,
0x3f800000,0x0,0x3f6a09a7,0xbecf7bca,0x3f2beb4a,0xbf3daef9,0x3ea09ae5,0xbf731447,0xbdc8bd36,0xbf7ec46d,0xbefc5d27,0xbf5ebe05,0xbf4d9f02,0xbf187fc0,0xbf79c79d,0xbe605c13,
0x3f800000,0x0,0x3f68bf3c,0xbed53641,0x3f273656,0xbf41d870,0x3e8e9a22,0xbf75dec6,0xbe164083,0xbf7d3aac,0xbf0b9a6b,0xbf5695e5,0xbf584853,0xbf08f59b,0xbf7dabcc,0xbe09cf86,
0x3f800000,0x0,0x3f676bd8,0xbedae880,0x3f226799,0xbf45e403,0x3e78cfcc,0xbf7853f8,0xbe47c5c2,0xbf7b14be,0xbf187fc0,0xbf4d9f02,0xbf61c598,0xbef15aea,0xbf7fb10f,0xbd48fb30,
0x3f800000,0x0,0x3f660f88,0xbee0924f,0x3f1d7fd1,0xbf49d112,0x3e541501,0xbf7a7302,0xbe78cfcc,0xbf7853f8,0xbf24d225,0xbf43e200,0xbf6a09a7,0xbecf7bca,0xbf7fd397,0x3d16c32c,
0x3f800000,0x0,0x3f64aa59,0xbee63375,0x3f187fc0,0xbf4d9f02,0x3e2f10a2,0xbf7c3b28,0xbe94a031,0xbf74fa0b,0xbf3085bb,0xbf396842,0xbf710908,0xbeac7cd4,0xbf7e1324,0x3dfab273,
0x3f800000,0x0,0x3f633c5a,0xbeebcbbb,0x3f13682a,0xbf514d3d,0x3e09cf86,0xbf7dabcc,0xbeac7cd4,0xbf710908,0xbf3b8f3b,0xbf2e3bde,0xbf76ba07,0xbe888e93,0xbf7a7302,0x3e541501,
0x3f800000,0x0,0x3f74fa0b,0xbe94a031,0x3f54db31,0xbf0e39da,0x3f226799,0xbf45e403,0x3ec3ef15,0xbf6c835e,0x3dc8bd36,0xbf7ec46d,0xbe47c5c2,0xbf7b14be,0xbef15aea,0xbf61c598,
0x3f800000,0x0,0x3f531849,0xbf10d3cd,0x3eb8442a,0xbf6ed89e,0xbe6c9a7f,0xbf791298,0xbf3daef9,0xbf2beb4a,0xbf7dabcc,0xbe09cf86,0xbf64aa59,0x3ee63375,0xbef6e0cb,0x3f604621,
0x3f800000,0x0,0x3f514d3d,0xbf13682a,0x3eac7cd4,0xbf710908,0xbe888e93,0xbf76ba07,0xbf45e403,0xbf226799,0xbf7f4e6d,0xbd96a905,0xbf5b941a,0x3f039c3d,0xbecf7bca,0x3f6a09a7,
0x3f800000,0x0,0x3f4f7a1f,0xbf15f6d9,0x3ea09ae5,0xbf731447,0xbe9aa086,0xbf740bdd,0xbf4d9f02,0xbf187fc0,0xbf7ffb11,0xbc490e90,0xbf514d3d,0x3f13682a,0xbea68f12,0x3f721352,
0x3f800000,0x0,0x3f4d9f02,0xbf187fc0,0x3e94a031,0xbf74fa0b,0xbeac7cd4,0xbf710908,0xbf54db31,0xbf0e39da,0xbf7fb10f,0x3d48fb30,0xbf45e403,0x3f226799,0xbe78cfcc,0x3f7853f8,
0x3f800000,0x0,0x3f4bbbf8,0xbf1b02c6,0x3e888e93,0xbf76ba07,0xbebe1d4a,0xbf6db293,0xbf5b941a,0xbf039c3d,0xbf7e70b0,0x3de1bc2e,0xbf396842,0x3f3085bb,0xbe22abb6,0x3f7cbfc9,
0x3f800000,0x0,0x3f49d112,0xbf1d7fd1,0x3e78cfcc,0xbf7853f8,0xbecf7bca,0xbf6a09a7,0xbf61c598,0xbef15aea,0xbf7c3b28,0x3e2f10a2,0xbf2beb4a,0x3f3daef9,0xbd96a905,0x3f7f4e6d,
0x3f800000,0x0,0x3f47de65,0xbf1ff6cb,0x3e605c13,0xbf79c79d,0xbee0924f,0xbf660f88,0xbf676bd8,0xbedae880,0xbf791298,0x3e6c9a7f,0xbf1d7fd1,0x3f49d112,0x3c490e90,0x3f7ffb11,
0x3f800000,0x0,0x3f800000,0x0,0x3f800000,0x0,0x3f800000,0x0,0x40000000,0x0,0x3f800000,0x0,0x3f800000,0x0,0x3f800000,0x0,
0x3f800000,0x0,0x3f7ffb11,0xbc490e90,0x3f7fec43,0xbcc90ab0,0x3f7fd397,0xbd16c32c,0x3fffb10f,0xbdc8fb30,0x3f7f84ab,0xbd7b2b74,0x3f7f4e6d,0xbd96a905,0x3f7f0e58,0xbdafb680,
0x3f800000,0x0,0x3f7fec43,0xbcc90ab0,0x3f7fb10f,0xbd48fb30,0x3f7f4e6d,0xbd96a905,0x3ffec46d,0xbe48bd36,0x3f7e1324,0xbdfab273,0x3f7d3aac,0xbe164083,0x3f7c3b28,0xbe2f10a2,
0x3f800000,0x0,0x3f7fd397,0xbd16c32c,0x3f7f4e6d,0xbd96a905,0x3f7e70b0,0xbde1bc2e,0x3ffd3aac,0xbe964083,0x3f7baccd,0xbe3b6ecf,0x3f79c79d,0xbe605c13,0x3f778bc5,0xbe827dc0,
0x3f800000,0x0,0x3f7fb10f,0xbd48fb30,0x3f7ec46d,0xbdc8bd36,0x3f7d3aac,0xbe164083,0x3ffb14be,0xbec7c5c2,0x3f7853f8,0xbe78cfcc,0x3f74fa0b,0xbe94a031,0x3f710908,0xbeac7cd4,
0x3f800000,0x0,0x3f7f84ab,0xbd7b2b74,0x3f7e1324,0xbdfab273,0x3f7baccd,0xbe3b6ecf,0x3ff853f8,0xbef8cfcc,0x3f740bdd,0xbe9aa086,0x3f6ed89e,0xbeb8442a,0x3f68bf3c,0xbed53641,
0x3f800000,0x0,0x3f7f4e6d,0xbd96a905,0x3f7d3aac,0xbe164083,0x3f79c79d,0xbe605c13,0x3ff4fa0b,0xbf14a031,0x3f6ed89e,0xbeb8442a,0x3f676bd8,0xbedae880,0x3f5ebe05,0xbefc5d27,
0x3f800000,0x0,0x3f7f0e58,0xbdafb680,0x3f7c3b28,0xbe2f10a2,0x3f778bc5,0xbe827dc0,0x3ff10908,0xbf2c7cd4,0x3f68bf3c,0xbed53641,0x3f5ebe05,0xbefc5d27,0x3f531849,0xbf10d3cd,
0x3f800000,0x0,0x3f7ec46d,0xbdc8bd36,0x3f7b14be,0xbe47c5c2,0x3f74fa0b,0xbe94a031,0x3fec835e,0xbf43ef15,0x3f61c598,0xbef15aea,0x3f54db31,0xbf0e39da,0x3f45e403,0xbf226799,
0x3f800000,0x0,0x3f7e70b0,0xbde1bc2e,0x3f79c79d,0xbe605c13,0x3f721352,0xbea68f12,0x3fe76bd8,0xbf5ae880,0x3f59f26a,0xbf064b82,0x3f49d112,0xbf1d7fd1,0x3f373a23,0xbf32c8c9,
0x3f800000,0x0,0x3f7e1324,0xbdfab273,0x3f7853f8,0xbe78cfcc,0x3f6ed89e,0xbeb8442a,0x3fe1c598,0xbf715aea,0x3f514d3d,0xbf13682a,0x3f3daef9,0xbf2beb4a,0x3f273656,0xbf41d870,
0x3f800000,0x0,0x3f7dabcc,0xbe09cf86,0x3f76ba07,0xbe888e93,0x3f6b4b0c,0xbec9b953,0x3fdb941a,0xbf839c3d,0x3f47de65,0xbf1ff6cb,0x3f3085bb,0xbf396842,0x3f15f6d9,0xbf4f7a1f,
0x3f800000,0x0,0x3f7d3aac,0xbe164083,0x3f74fa0b,0xbe94a031,0x3f676bd8,0xbedae880,0x3fd4db31,0xbf8e39da,0x3f3daef9,0xbf2beb4a,0x3f226799,0xbf45e403,0x3f039c3d,0xbf5b941a,
0x3f800000,0x0,0x3f7cbfc9,0xbe22abb6,0x3f731447,0xbea09ae5,0x3f633c5a,0xbeebcbbb,0x3fcd9f02,0xbf987fc0,0x3f32c8c9,0xbf373a23,0x3f13682a,0xbf514d3d,0x3ee0924f,0xbf660f88,
0x3f800000,0x0,0x3f7c3b28,0xbe2f10a2,0x3f710908,0xbeac7cd4,0x3f5ebe05,0xbefc5d27,0x3fc5e403,0xbfa26799,0x3f273656,0xbf41d870,0x3f039c3d,0xbf5b941a,0x3eb8442a,0xbf6ed89e,
0x3f800000,0x0,0x3f7baccd,0xbe3b6ecf,0x3f6ed89e,0xbeb8442a,0x3f59f26a,0xbf064b82,0x3fbdaef9,0xbfabeb4a,0x3f1b02c6,0xbf4bbbf8,0x3ee63375,0xbf64aa59,0x3e8e9a22,0xbf75dec6,
0x3f800000,0x0,0x3f7b14be,0xbe47c5c2,0x3f6c835e,0xbec3ef15,0x3f54db31,0xbf0e39da,0x3fb504f3,0xbfb504f3,0x3f0e39da,0xbf54db31,0x3ec3ef15,0xbf6c835e,0x3e47c5c2,0xbf7b14be,
0x3f800000,0x0,0x3f7a7302,0xbe541501,0x3f6a09a7,0xbecf7bca,0x3f4f7a1f,0xbf15f6d9,0x3fabeb4a,0xbfbdaef9,0x3f00e7e4,0xbf5d2d53,0x3ea09ae5,0xbf731447,0x3de1bc2e,0xbf7e70b0,
0x3f800000,0x0,0x3f79c79d,0xbe605c13,0x3f676bd8,0xbedae880,0x3f49d112,0xbf1d7fd1,0x3fa26799,0xbfc5e403,0x3ee63375,0xbf64aa59,0x3e78cfcc,0xbf7853f8,0x3cc90ab0,0xbf7fec43,
0x3f800000,0x0,0x3f791298,0xbe6c9a7f,0x3f64aa59,0xbee63375,0x3f43e200,0xbf24d225,0x3f987fc0,0xbfcd9f02,0x3ec9b953,0xbf6b4b0c,0x3e2f10a2,0xbf7c3b28,0xbd7b2b74,0xbf7f84ab,
0x3f800000,0x0,0x3f7853f8,0xbe78cfcc,0x3f61c598,0xbef15aea,0x3f3daef9,0xbf2beb4a,0x3f8e39da,0xbfd4db31,0x3eac7cd4,0xbf710908,0x3dc8bd36,0xbf7ec46d,0xbe164083,0xbf7d3aac,
0x3f800000,0x0,0x3f778bc5,0xbe827dc0,0x3f5ebe05,0xbefc5d27,0x3f373a23,0xbf32c8c9,0x3f839c3d,0xbfdb941a,0x3e8e9a22,0xbf75dec6,0x3cc90ab0,0xbf7fec43,0xbe6c9a7f,0xbf791298,
0x3f800000,0x0,0x3f76ba07,0xbe888e93,0x3f5b941a,0xbf039c3d,0x3f3085bb,0xbf396842,0x3f715aea,0xbfe1c598,0x3e605c13,0xbf79c79d,0xbd48fb30,0xbf7fb10f,0xbea09ae5,0xbf731447,
0x3f800000,0x0,0x3f75dec6,0xbe8e9a22,0x3f584853,0xbf08f59b,0x3f299415,0xbf3fc767,0x3f5ae880,0xbfe76bd8,0x3e22abb6,0xbf7cbfc9,0xbdfab273,0xbf7e1324,0xbec9b953,0xbf6b4b0c,
0x3f800000,0x0,0x3f74fa0b,0xbe94a031,0x3f54db31,0xbf0e39da,0x3f226799,0xbf45e403,0x3f43ef15,0xbfec835e,0x3dc8bd36,0xbf7ec46d,0xbe47c5c2,0xbf7b14be,0xbef15aea,0xbf61c598,
0x3f800000,0x0,0x3f740bdd,0xbe9aa086,0x3f514d3d,0xbf13682a,0x3f1b02c6,0xbf4bbbf8,0x3f2c7cd4,0xbff10908,0x3d16c32c,0xbf7fd397,0xbe888e93,0xbf76ba07,0xbf0b9a6b,0xbf5695e5,
0x3f800000,0x0,0x3f731447,0xbea09ae5,0x3f4d9f02,0xbf187fc0,0x3f13682a,0xbf514d3d,0x3f14a031,0xbff4fa0b,0xbcc90ab0,0xbf7fec43,0xbeac7cd4,0xbf710908,0xbf1d7fd1,0xbf49d112,
0x3f800000,0x0,0x3f721352,0xbea68f12,0x3f49d112,0xbf1d7fd1,0x3f0b9a6b,0xbf5695e5,0x3ef8cfcc,0xbff853f8,0xbdafb680,0xbf7f0e58,0xbecf7bca,0xbf6a09a7,0xbf2e3bde,0xbf3b8f3b,
0x3f800000,0x0,0x3f710908,0xbeac7cd4,0x3f45e403,0xbf226799,0x3f039c3d,0xbf5b941a,0x3ec7c5c2,0xbffb14be,0xbe164083,0xbf7d3aac,0xbef15aea,0xbf61c598,0xbf3daef9,0xbf2beb4a,
0x3f800000,0x0,0x3f6ff573,0xbeb263ef,0x3f41d870,0xbf273656,0x3ef6e0cb,0xbf604621,0x3e964083,0xbffd3aac,0xbe541501,0xbf7a7302,0xbf08f59b,0xbf584853,0xbf4bbbf8,0xbf1b02c6,
0x3f800000,0x0,0x3f6ed89e,0xbeb8442a,0x3f3daef9,0xbf2beb4a,0x3ee63375,0xbf64aa59,0x3e48bd36,0xbffec46d,0xbe888e93,0xbf76ba07,0xbf187fc0,0xbf4d9f02,0xbf584853,0xbf08f59b,
0x3f800000,0x0,0x3f6db293,0xbebe1d4a,0x3f396842,0xbf3085bb,0x3ed53641,0xbf68bf3c,0x3dc8fb30,0xbfffb10f,0xbea68f12,0xbf721352,0xbf273656,0xbf41d870,0xbf633c5a,0xbeebcbbb,
0x3f800000,0x0,0x3f7fffb1,0xbb490fc6,0x3f7ffec4,0xbbc90f88,0x3f7ffd39,0xbc16cb58,0x3ffffb11,0xbcc90e90,0x3f7ff84a,0xbc7b514b,0x3f7ff4e6,0xbc96c9b6,0x3f7ff0e3,0xbcafea69,
0x3f800000,0x0,0x3f7ff84a,0xbc7b514b,0x3f7fe129,0xbcfb49ba,0x3f7fba9e,0xbd3c6dd5,0x3fff84ab,0xbdfb2b74,0x3f7f3f54,0xbd9cecf9,0x3f7eea9d,0xbdbc3ac3,0x3f7e868b,0xbddb7d37,
0x3f800000,0x0,0x3f7fe705,0xbce22a7a,0x3f7f9c18,0xbd621469,0x3f7f1f49,0xbda973ba,0x3ffe70b0,0xbe61bc2e,0x3f7d906e,0xbe0cec4a,0x3f7c7eb0,0xbe28defc,0x3f7b3bab,0xbe44b0b9,
0x3f800000,0x0,0x3f7fcbe2,0xbd2351cb,0x3f7f2f9d,0xbda3308c,0x3f7e2b72,0xbdf475c0,0x3ffcbfc9,0xbea2abb6,0x3f7aed37,0xbe4ada4f,0x3f78b47b,0xbe72b651,0x3f76167a,0xbe8d17c0,
0x3f800000,0x0,0x3f7fa6e3,0xbd55880e,0x3f7e9bc9,0xbdd53db9,0x3f7cdf6c,0xbe1f917b,0x3ffa7302,0xbed41501,0x3f77583a,0xbe840270,0x3f73913f,0xbe9d9e78,0x3f6f20b0,0xbeb6ccc3,
0x3f800000,0x0,0x3f7f7808,0xbd83db0a,0x3f7de0b1,0xbe039502,0x3f7b3bab,0xbe44b0b9,0x3ff78bc5,0xbf027dc0,0x3f72d4eb,0xbea21887,0x3f6d1c1d,0xbec1071e,0x3f666771,0xbedf28a9,
0x3f800000,0x0,0x3f7f3f54,0xbd9cecf9,0x3f7cfe73,0xbe1c76de,0x3f7940c0,0xbe698bba,0x3ff40bdd,0xbf1aa086,0x3f6d67a1,0xbebf926f,0x3f655e0b,0xbee363fa,0x3f5bfb34,0xbf02ef9f,
0x3f800000,0x0,0x3f7efcc9,0xbdb5f8da,0x3f7bf531,0xbe354098,0x3f76ef5b,0xbe870ada,0x3feff573,0xbf3263ef,0x3f671599,0xbedc53c1,0x3f5c61c7,0xbf0242b1,0x3f4fefa8,0xbf1553b7,
0x3f800000,0x0,0x3f7eb069,0xbdcefdb7,0x3f7ac516,0xbe4dee60,0x3f74484b,0xbe9920fe,0x3feb4b0c,0xbf49b953,0x3f5fe4e9,0xbef840c8,0x3f5233c6,0xbf121eb0,0x3f425b89,0xbf269de3,
0x3f800000,0x0,0x3f7e5a38,0xbde7fa9a,0x3f796e4e,0xbe667c66,0x3f714c7a,0xbeab0201,0x3fe60f88,0xbf60924f,0x3f57dc7f,0xbf099f4e,0x3f46e22a,0xbf212ff9,0x3f33587a,0xbf36ad7f,
0x3f800000,0x0,0x3f7dfa38,0xbe007745,0x3f77f110,0xbe7ee6e1,0x3f6dfcf2,0xbebca7af,0x3fe04621,0xbf76e0cb,0x3f4f0417,0xbf16999f,0x3f3a7ca4,0xbf2f61a5,0x3f2302d3,0xbf456439,
0x3f800000,0x0,0x3f7d906e,0xbe0cec4a,0x3f764d97,0xbe8b9507,0x3f6a5ad9,0xbece0bea,0x3fd9f26a,0xbf864b82,0x3f456439,0xbf2302d3,0x3f2d1469,0xbf3ca003,0x3f11796b,0xbf52a649,
0x3f800000,0x0,0x3f7d1cdd,0xbe195be0,0x3f748422,0xbe97a117,0x3f666771,0xbedf28a9,0x3fd31849,0xbf90d3cd,0x3f3b0629,0xbf2ecef7,0x3f1ebc12,0xbf48d8b3,0x3efdbabb,0xbf5e5aa6,
0x3f800000,0x0,0x3f7c9f8a,0xbe25c58c,0x3f7294f8,0xbea395c5,0x3f62241a,0xbeeff7fb,0x3fcbbbf8,0xbf9b02c6,0x3f2ff3e6,0xbf39f2ac,0x3f0f8784,0xbf53fac3,0x3ed6a399,0xbf686b39,
0x3f800000,0x0,0x3f7c187a,0xbe3228d4,0x3f708066,0xbeaf713a,0x3f5d924d,0xbf003a06,0x3fc3e200,0xbfa4d225,0x3f24381a,0xbf446337,0x3eff17b2,0xbf5df6be,0x3eadf73c,0xbf70c501,
0x3f800000,0x0,0x3f7b87b2,0xbe3e853e,0x3f6e46be,0xbebb31a0,0x3f58b3a1,0xbf084b92,0x3fbb8f3b,0xbfae3bde,0x3f17de12,0xbf4e1689,0x3eddbe79,0xbf66becc,0x3e840270,0xbf77583a,
0x3f800000,0x0,0x3f7aed37,0xbe4ada4f,0x3f6be858,0xbec6d529,0x3f5389c7,0xbf102dd5,0x3fb2c8c9,0xbfb73a23,0x3f0af1b7,0xbf570348,0x3ebb31a0,0xbf6e46be,0x3e3228d4,0xbf7c187a,
0x3f800000,0x0,0x3f7a4910,0xbe57278f,0x3f696591,0xbed25a09,0x3f4e1689,0xbf17de12,0x3fa99415,0xbfbfc767,0x3efafef7,0xbf5f20db,0x3e97a117,0xbf748422,0x3db5f8da,0xbf7efcc9,
0x3f800000,0x0,0x3f799b43,0xbe636c83,0x3f66becc,0xbeddbe79,0x3f485bca,0xbf1f599f,0x3f9ff6cb,0xbfc7de65,0x3edf28a9,0xbf666771,0x3e667c66,0xbf796e4e,0x3b490fc6,0xbf7fffb1,
0x3f800000,0x0,0x3f78e3d6,0xbe6fa8b2,0x3f63f473,0xbee900b7,0x3f425b89,0xbf269de3,0x3f95f6d9,0xbfcf7a1f,0x3ec27b55,0xbf6cd007,0x3e1c76de,0xbf7cfe73,0xbda973ba,0xbf7f1f49,
0x3f800000,0x0,0x3f7822d1,0xbe7bdba4,0x3f6106f2,0xbef41f07,0x3f3c17d9,0xbf2da859,0x3f8b9a6b,0xbfd695e5,0x3ea5129f,0xbf725470,0x3da3308c,0xbf7f2f9d,0xbe2bf804,0xbf7c5d3a,
0x3f800000,0x0,0x3f77583a,0xbe840270,0x3f5df6be,0xbeff17b2,0x3f3592e7,0xbf34768f,0x3f80e7e4,0xbfdd2d53,0x3e870ada,0xbf76ef5b,0x3bc90f88,0xbf7ffec4,0xbe80f8c0,0xbf77beb7,
0x3f800000,0x0,0x3f76841b,0xbe8a11f7,0x3f5ac450,0xbf04f484,0x3f2ecef7,0xbf3b0629,0x3f6bcbbb,0xbfe33c5a,0x3e5101f1,0xbf7a9c59,0xbd8a200a,0xbf7f6ac7,0xbeab0201,0xbf714c7a,
0x3f800000,0x0,0x3f75a67b,0xbe901c2c,0x3f577026,0xbf0a48ad,0x3f27ce61,0xbf4154e1,0x3f553641,0xbfe8bf3c,0x3e1324ca,0xbf7d57de,0xbe1008b7,0xbf7d7474,0xbed3c867,0xbf6912ae,
0x3f800000,0x0,0x3f74bf62,0xbe9620d2,0x3f53fac3,0xbf0f8784,0x3f209393,0xbf476085,0x3f3e1d4a,0xbfedb293,0x3da973ba,0xbf7f1f49,0xbe5a3997,0xbf7a1e84,0xbefafef7,0xbf5f20db,
0x3f800000,0x0,0x3f73ced9,0xbe9c1faf,0x3f5064af,0xbf14b039,0x3f19210f,0xbf4d26fd,0x3f268f12,0xbff21352,0x3cafea69,0xbf7ff0e3,0xbe919ddd,0xbf756d97,0xbf102dd5,0xbf5389c7,
0x3f800000,0x0,0x3f72d4eb,0xbea21887,0x3f4cae79,0xbf19c200,0x3f11796b,0xbf52a649,0x3f0e9a22,0xbff5dec6,0xbd2351cb,0xbf7fcbe2,0xbeb554ec,0xbf6f6830,0xbf21cbfb,0xbf466354,
0x3f800000,0x0,0x3f71d19f,0xbea80b1f,0x3f48d8b3,0xbf1ebc12,0x3f099f4e,0xbf57dc7f,0x3eec9a7f,0xbff91298,0xbdcefdb7,0xbf7eb069,0xbed8106b,0xbf6816a8,0xbf3238aa,0xbf37c655,
0x3f800000,0x0,0x3f70c501,0xbeadf73c,0x3f44e3f5,0xbf239da9,0x3f019573,0xbf5cc7d1,0x3ebb6ecf,0xbffbaccd,0xbe25c58c,0xbf7c9f8a,0xbef9a02d,0xbf5f8327,0xbf4154e1,0xbf27ce61,
0x3f800000,0x0,0x3f6faf1b,0xbeb3dca5,0x3f40d0da,0xbf286605,0x3ef2bd43,0xbf61668a,0x3e89cf86,0xbffdabcc,0xbe636c83,0xbf799b43,0xbf0cead0,0xbf55b993,0xbf4f0417,0xbf16999f,
0x3f800000,0x0,0x3f6e8ff8,0xbeb9bb1e,0x3f3ca003,0xbf2d1469,0x3ee1fb6a,0xbf65b710,0x3e2fb680,0xbfff0e58,0xbe901c2c,0xbf75a67b,0xbf1c420c,0xbf4ac77f,0xbf5b2c79,0xbf044889,
0x3f800000,0x0,0x3f6d67a1,0xbebf926f,0x3f385216,0xbf31a81d,0x3ed0eb2a,0xbf69b7e4,0x3d96c32c,0xbfffd397,0xbeadf73c,0xbf70c501,0xbf2ac082,0xbf3ebc1b,0xbf65b710,0xbee1fb6a,
0x3f800000,0x0,0x3f7ffec4,0xbbc90f88,0x3f7ffb11,0xbc490e90,0x3f7ff4e6,0xbc96c9b6,0x3fffec43,0xbd490ab0,0x3f7fe129,0xbcfb49ba,0x3f7fd397,0xbd16c32c,0x3f7fc38f,0xbd2fe007,
0x3f800000,0x0,0x3f7ff4e6,0xbc96c9b6,0x3f7fd397,0xbd16c32c,0x3f7f9c18,0xbd621469,0x3fff4e6d,0xbe16a905,0x3f7eea9d,0xbdbc3ac3,0x3f7e70b0,0xbde1bc2e,0x3f7de0b1,0xbe039502,
0x3f800000,0x0,0x3f7fe129,0xbcfb49ba,0x3f7f84ab,0xbd7b2b74,0x3f7eea9d,0xbdbc3ac3,0x3ffe1324,0xbe7ab273,0x3f7cfe73,0xbe1c76de,0x3f7baccd,0xbe3b6ecf,0x3f7a1e84,0xbe5a3997,
0x3f800000,0x0,0x3f7fc38f,0xbd2fe007,0x3f7f0e58,0xbdafb680,0x3f7de0b1,0xbe039502,0x3ffc3b28,0xbeaf10a2,0x3f7a1e84,0xbe5a3997,0x3f778bc5,0xbe827dc0,0x3f748422,0xbe97a117,
0x3f800000,0x0,0x3f7f9c18,0xbd621469,0x3f7e70b0,0xbde1bc2e,0x3f7c7eb0,0xbe28defc,0x3ff9c79d,0xbee05c13,0x3f764d97,0xbe8b9507,0x3f721352,0xbea68f12,0x3f6d1c1d,0xbec1071e,
0x3f800000,0x0,0x3f7f6ac7,0xbd8a200a,0x3f7dabcc,0xbe09cf86,0x3f7ac516,0xbe4dee60,0x3ff6ba07,0xbf088e93,0x3f718f57,0xbea986c4,0x3f6b4b0c,0xbec9b953,0x3f63f473,0xbee900b7,
0x3f800000,0x0,0x3f7f2f9d,0xbda3308c,0x3f7cbfc9,0xbe22abb6,0x3f78b47b,0xbe72b651,0x3ff31447,0xbf209ae5,0x3f6be858,0xbec6d529,0x3f633c5a,0xbeebcbbb,0x3f591e6a,0xbf07a136,
0x3f800000,0x0,0x3f7eea9d,0xbdbc3ac3,0x3f7baccd,0xbe3b6ecf,0x3f764d97,0xbe8b9507,0x3feed89e,0xbf38442a,0x3f655e0b,0xbee363fa,0x3f59f26a,0xbf064b82,0x3f4cae79,0xbf19c200,
0x3f800000,0x0,0x3f7e9bc9,0xbdd53db9,0x3f7a7302,0xbe541501,0x3f73913f,0xbe9d9e78,0x3fea09a7,0xbf4f7bca,0x3f5df6be,0xbeff17b2,0x3f4f7a1f,0xbf15f6d9,0x3f3ebc1b,0xbf2ac082,
0x3f800000,0x0,0x3f7e4323,0xbdee3876,0x3f791298,0xbe6c9a7f,0x3f708066,0xbeaf713a,0x3fe4aa59,0xbf663375,0x3f55b993,0xbf0cead0,0x3f43e200,0xbf24d225,0x3f2f61a5,0xbf3a7ca4,
0x3f800000,0x0,0x3f7de0b1,0xbe039502,0x3f778bc5,0xbe827dc0,0x3f6d1c1d,0xbec1071e,0x3fdebe05,0xbf7c5d27,0x3f4cae79,0xbf19c200,0x3f373a23,0xbf32c8c9,0x3f1ebc12,0xbf48d8b3,
0x3f800000,0x0,0x3f7d7474,0xbe1008b7,0x3f75dec6,0xbe8e9a22,0x3f696591,0xbed25a09,0x3fd84853,0xbf88f59b,0x3f42de29,0xbf26050a,0x3f299415,0xbf3fc767,0x3f0cead0,0xbf55b993,
0x3f800000,0x0,0x3f7cfe73,0xbe1c76de,0x3f740bdd,0xbe9aa086,0x3f655e0b,0xbee363fa,0x3fd14d3d,0xbf93682a,0x3f385216,0xbf31a81d,0x3f1b02c6,0xbf4bbbf8,0x3ef41f07,0xbf6106f2,
0x3f800000,0x0,0x3f7c7eb0,0xbe28defc,0x3f721352,0xbea68f12,0x3f6106f2,0xbef41f07,0x3fc9d112,0xbf9d7fd1,0x3f2d1469,0xbf3ca003,0x3f0b9a6b,0xbf5695e5,0x3ecc9b8b,0xbf6aab7b,
0x3f800000,0x0,0x3f7bf531,0xbe354098,0x3f6ff573,0xbeb263ef,0x3f5c61c7,0xbf0242b1,0x3fc1d870,0xbfa73656,0x3f212ff9,0xbf46e22a,0x3ef6e0cb,0xbf604621,0x3ea395c5,0xbf7294f8,
0x3f800000,0x0,0x3f7b61fc,0xbe419b37,0x3f6db293,0xbebe1d4a,0x3f577026,0xbf0a48ad,0x3fb96842,0xbfb085bb,0x3f14b039,0xbf5064af,0x3ed53641,0xbf68bf3c,0x3e72b651,0xbf78b47b,
0x3f800000,0x0,0x3f7ac516,0xbe4dee60,0x3f6b4b0c,0xbec9b953,0x3f5233c6,0xbf121eb0,0x3fb085bb,0xbfb96842,0x3f07a136,0xbf591e6a,0x3eb263ef,0xbf6ff573,0x3e1c76de,0xbf7cfe73,
0x3f800000,0x0,0x3f7a1e84,0xbe5a3997,0x3f68bf3c,0xbed53641,0x3f4cae79,0xbf19c200,0x3fa73656,0xbfc1d870,0x3ef41f07,0xbf6106f2,0x3e8e9a22,0xbf75dec6,0x3d8a200a,0xbf7f6ac7,
0x3f800000,0x0,0x3f796e4e,0xbe667c66,0x3f660f88,0xbee0924f,0x3f46e22a,0xbf212ff9,0x3f9d7fd1,0xbfc9d112,0x3ed8106b,0xbf6816a8,0x3e541501,0xbf7a7302,0xbc96c9b6,0xbf7ff4e6,
0x3f800000,0x0,0x3f78b47b,0xbe72b651,0x3f633c5a,0xbeebcbbb,0x3f40d0da,0xbf286605,0x3f93682a,0xbfd14d3d,0x3ebb31a0,0xbf6e46be,0x3e09cf86,0xbf7dabcc,0xbdd53db9,0xbf7e9bc9,
0x3f800000,0x0,0x3f77f110,0xbe7ee6e1,0x3f604621,0xbef6e0cb,0x3f3a7ca4,0xbf2f61a5,0x3f88f59b,0xbfd84853,0x3e9d9e78,0xbf73913f,0x3d7b2b74,0xbf7f84ab,0xbe419b37,0xbf7b61fc,
0x3f800000,0x0,0x3f772417,0xbe8586ce,0x3f5d2d53,0xbf00e7e4,0x3f33e7bc,0xbf36206c,0x3f7c5d27,0xbfdebe05,0x3e7ee6e1,0xbf77f110,0xbc490e90,0xbf7ffb11,0xbe8b9507,0xbf764d97,
0x3f800000,0x0,0x3f764d97,0xbe8b9507,0x3f59f26a,0xbf064b82,0x3f2d1469,0xbf3ca003,0x3f663375,0xbfe4aa59,0x3e419b37,0xbf7b61fc,0xbdafb680,0xbf7f0e58,0xbeb554ec,0xbf6f6830,
0x3f800000,0x0,0x3f756d97,0xbe919ddd,0x3f5695e5,0xbf0b9a6b,0x3f26050a,0xbf42de29,0x3f4f7bca,0xbfea09a7,0x3e039502,0xbf7de0b1,0xbe22abb6,0xbf7cbfc9,0xbeddbe79,0xbf66becc,
0x3f800000,0x0,0x3f748422,0xbe97a117,0x3f531849,0xbf10d3cd,0x3f1ebc12,0xbf48d8b3,0x3f38442a,0xbfeed89e,0x3d8a200a,0xbf7f6ac7,0xbe6c9a7f,0xbf791298,0xbf0242b1,0xbf5c61c7,
0x3f800000,0x0,0x3f73913f,0xbe9d9e78,0x3f4f7a1f,0xbf15f6d9,0x3f173c07,0xbf4e8d90,0x3f209ae5,0xbff31447,0x3bc90f88,0xbf7ffec4,0xbe9aa086,0xbf740bdd,0xbf14b039,0xbf5064af,
0x3f800000,0x0,0x3f7294f8,0xbea395c5,0x3f4bbbf8,0xbf1b02c6,0x3f0f8784,0xbf53fac3,0x3f088e93,0xbff6ba07,0xbd621469,0xbf7f9c18,0xbebe1d4a,0xbf6db293,0xbf26050a,0xbf42de29,
0x3f800000,0x0,0x3f718f57,0xbea986c4,0x3f47de65,0xbf1ff6cb,0x3f07a136,0xbf591e6a,0x3ee05c13,0xbff9c79d,0xbdee3876,0xbf7e4323,0xbee0924f,0xbf660f88,0xbf36206c,0xbf33e7bc,
0x3f800000,0x0,0x3f708066,0xbeaf713a,0x3f43e200,0xbf24d225,0x3eff17b2,0xbf5df6be,0x3eaf10a2,0xbffc3b28,0xbe354098,0xbf7bf531,0xbf00e7e4,0xbf5d2d53,0xbf44e3f5,0xbf239da9,
0x3f800000,0x0,0x3f6f6830,0xbeb554ec,0x3f3fc767,0xbf299415,0x3eee9479,0xbf628210,0x3e7ab273,0xbffe1324,0xbe72b651,0xbf78b47b,0xbf10d3cd,0xbf531849,0xbf5233c6,0xbf121eb0,
0x3f800000,0x0,0x3f6e46be,0xbebb31a0,0x3f3b8f3b,0xbf2e3bde,0x3eddbe79,0xbf66becc,0x3e16a905,0xbfff4e6d,0xbe97a117,0xbf748422,0xbf1ff6cb,0xbf47de65,0xbf5df6be,0xbeff17b2,
0x3f800000,0x0,0x3f6d1c1d,0xbec1071e,0x3f373a23,0xbf32c8c9,0x3ecc9b8b,0xbf6aab7b,0x3d490ab0,0xbfffec43,0xbeb554ec,0xbf6f6830,0xbf2e3bde,0xbf3b8f3b,0xbf6816a8,0xbed8106b,
0x3f800000,0x0,0x3f7ffd39,0xbc16cb58,0x3f7ff4e6,0xbc96c9b6,0x3f7fe705,0xbce22a7a,0x3fffd397,0xbd96c32c,0x3f7fba9e,0xbd3c6dd5,0x3f7f9c18,0xbd621469,0x3f7f7808,0xbd83db0a,
0x3f800000,0x0,0x3f7ff0e3,0xbcafea69,0x3f7fc38f,0xbd2fe007,0x3f7f7808,0xbd83db0a,0x3fff0e58,0xbe2fb680,0x3f7e868b,0xbddb7d37,0x3f7de0b1,0xbe039502,0x3f7d1cdd,0xbe195be0,
0x3f800000,0x0,0x3f7fdaaf,0xbd0a342f,0x3f7f6ac7,0xbd8a200a,0x3f7eb069,0xbdcefdb7,0x3ffdabcc,0xbe89cf86,0x3f7c5d3a,0xbe2bf804,0x3f7ac516,0xbe4dee60,0x3f78e3d6,0xbe6fa8b2,
0x3f800000,0x0,0x3f7fba9e,0xbd3c6dd5,0x3f7eea9d,0xbdbc3ac3,0x3f7d906e,0xbe0cec4a,0x3ffbaccd,0xbebb6ecf,0x3f7940c0,0xbe698bba,0x3f764d97,0xbe8b9507,0x3f72d4eb,0xbea21887,
0x3f800000,0x0,0x3f7f90b1,0xbd6ea038,0x3f7e4323,0xbdee3876,0x3f7c187a,0xbe3228d4,0x3ff91298,0xbeec9a7f,0x3f75341d,0xbe931f35,0x3f708066,0xbeaf713a,0x3f6afb8c,0xbecb2aae,
0x3f800000,0x0,0x3f7f5ce9,0xbd9064b4,0x3f7d7474,0xbe1008b7,0x3f7a4910,0xbe57278f,0x3ff5dec6,0xbf0e9a22,0x3f703b37,0xbeb0eacb,0x3f696591,0xbed25a09,0x3f61668a,0xbef2bd43,
0x3f800000,0x0,0x3f7f1f49,0xbda973ba,0x3f7c7eb0,0xbe28defc,0x3f7822d1,0xbe7bdba4,0x3ff21352,0xbf268f12,0x3f6a5ad9,0xbece0bea,0x3f6106f2,0xbef41f07,0x3f5627fe,0xbf0c42c9,
0x3f800000,0x0,0x3f7ed7d4,0xbdc27c39,0x3f7b61fc,0xbe419b37,0x3f75a67b,0xbe901c2c,0x3fedb293,0xbf3e1d4a,0x3f6398ac,0xbeea6681,0x3f577026,0xbf0a48ad,0x3f495521,0xbf1e1e22,
0x3f800000,0x0,0x3f7e868b,0xbddb7d37,0x3f7a1e84,0xbe5a3997,0x3f72d4eb,0xbea21887,0x3fe8bf3c,0xbf553641,0x3f5bfb34,0xbf02ef9f,0x3f4cae79,0xbf19c200,0x3f3b0629,0xbf2ecef7,
0x3f800000,0x0,0x3f7e2b72,0xbdf475c0,0x3f78b47b,0xbe72b651,0x3f6faf1b,0xbeb3dca5,0x3fe33c5a,0xbf6bcbbb,0x3f5389c7,0xbf102dd5,0x3f40d0da,0xbf286605,0x3f2b561b,0xbf3e35c5,
0x3f800000,0x0,0x3f7dc68c,0xbe06b26e,0x3f772417,0xbe8586ce,0x3f6c3624,0xbec5625c,0x3fdd2d53,0xbf80e7e4,0x3f4a4c87,0xbf1ce11f,0x3f33e7bc,0xbf36206c,0x3f1a6293,0xbf4c3578,
0x3f800000,0x0,0x3f7d57de,0xbe1324ca,0x3f756d97,0xbe919ddd,0x3f686b39,0xbed6a399,0x3fd695e5,0xbf8b9a6b,0x3f404c5c,0xbf28fd41,0x3f26050a,0xbf42de29,0x3f084b92,0xbf58b3a1,
0x3f800000,0x0,0x3f7cdf6c,0xbe1f917b,0x3f73913f,0xbe9d9e78,0x3f644fac,0xbee79a5d,0x3fcf7a1f,0xbf95f6d9,0x3f3592e7,0xbf34768f,0x3f173c07,0xbf4e8d90,0x3eea6681,0xbf6398ac,
0x3f800000,0x0,0x3f7c5d3a,0xbe2bf804,0x3f718f57,0xbea986c4,0x3f5fe4e9,0xbef840c8,0x3fc7de65,0xbf9ff6cb,0x3f2a2a80,0xbf3f41fc,0x3f07a136,0xbf591e6a,0x3ec27b55,0xbf6cd007,
0x3f800000,0x0,0x3f7bd14d,0xbe3857ec,0x3f6f6830,0xbeb554ec,0x3f5b2c79,0xbf044889,0x3fbfc767,0xbfa99415,0x3f1e1e22,0xbf495521,0x3eee9479,0xbf628210,0x3e9920fe,0xbf74484b,
0x3f800000,0x0,0x3f7b3bab,0xbe44b0b9,0x3f6d1c1d,0xbec1071e,0x3f5627fe,0xbf0c42c9,0x3fb73a23,0xbfb2c8c9,0x3f11796b,0xbf52a649,0x3ecc9b8b,0xbf6aab7b,0x3e5d4b1a,0xbf79f35e,
0x3f800000,0x0,0x3f7a9c59,0xbe5101f1,0x3f6aab7b,0xbecc9b8b,0x3f50d937,0xbf140c5f,0x3fae3bde,0xbfbb8f3b,0x3f044889,0xbf5b2c79,0x3ea986c4,0xbf718f57,0x3e06b26e,0xbf7dc68c,
0x3f800000,0x0,0x3f79f35e,0xbe5d4b1a,0x3f6816a8,0xbed8106b,0x3f4b41fa,0xbf1ba299,0x3fa4d225,0xbfc3e200,0x3eed3063,0xbf62df7b,0x3e8586ce,0xbf772417,0x3d3c6dd5,0xbf7fba9e,
0x3f800000,0x0,0x3f7940c0,0xbe698bba,0x3f655e0b,0xbee363fa,0x3f456439,0xbf2302d3,0x3f9b02c6,0xbfcbbbf8,0x3ed0eb2a,0xbf69b7e4,0x3e419b37,0xbf7b61fc,0xbd2351cb,0xbf7fcbe2,
0x3f800000,0x0,0x3f788486,0xbe75c35a,0x3f628210,0xbeee9479,0x3f3f41fc,0xbf2a2a80,0x3f90d3cd,0xbfd31849,0x3eb3dca5,0xbf6faf1b,0x3dee3876,0xbf7e4323,0xbe007745,0xbf7dfa38,
0x3f800000,0x0,0x3f77beb7,0xbe80f8c0,0x3f5f8327,0xbef9a02d,0x3f38dd65,0xbf311722,0x3f864b82,0xbfd9f26a,0x3e9620d2,0xbf74bf62,0x3d2fe007,0xbf7fc38f,0xbe57278f,0xbf7a4910,
0x3f800000,0x0,0x3f76ef5b,0xbe870ada,0x3f5c61c7,0xbf0242b1,0x3f3238aa,0xbf37c655,0x3f76e0cb,0xbfe04621,0x3e6fa8b2,0xbf78e3d6,0xbcfb49ba,0xbf7fe129,0xbe9620d2,0xbf74bf62,
0x3f800000,0x0,0x3f76167a,0xbe8d17c0,0x3f591e6a,0xbf07a136,0x3f2b561b,0xbf3e35c5,0x3f60924f,0xbfe60f88,0x3e3228d4,0xbf7c187a,0xbdd53db9,0xbf7e9bc9,0xbebf926f,0xbf6d67a1,
0x3f800000,0x0,0x3f75341d,0xbe931f35,0x3f55b993,0xbf0cead0,0x3f24381a,0xbf446337,0x3f49b953,0xbfeb4b0c,0x3de7fa9a,0xbf7e5a38,0xbe354098,0xbf7bf531,0xbee79a5d,0xbf644fac,
0x3f800000,0x0,0x3f74484b,0xbe9920fe,0x3f5233c6,0xbf121eb0,0x3f1ce11f,0xbf4a4c87,0x3f3263ef,0xbfeff573,0x3d55880e,0xbf7fa6e3,0xbe7ee6e1,0xbf77f110,0xbf06f686,0xbf5988ad,
0x3f800000,0x0,0x3f73530e,0xbe9f1cdf,0x3f4e8d90,0xbf173c07,0x3f1553b7,0xbf4fefa8,0x3f1aa086,0xbff40bdd,0xbc16cb58,0xbf7ffd39,0xbea395c5,0xbf7294f8,0xbf19210f,0xbf4d26fd,
0x3f800000,0x0,0x3f725470,0xbea5129f,0x3f4ac77f,0xbf1c420c,0x3f0d9281,0xbf554aa4,0x3f027dc0,0xbff78bc5,0xbd9064b4,0xbf7f5ce9,0xbec6d529,0xbf6be858,0xbf2a2a80,0xbf3f41fc,
0x3f800000,0x0,0x3f714c7a,0xbeab0201,0x3f46e22a,0xbf212ff9,0x3f05a02c,0xbf5a5ba0,0x3ed41501,0xbffa7302,0xbe06b26e,0xbf7dc68c,0xbee900b7,0xbf63f473,0xbf39f2ac,0xbf2ff3e6,
0x3f800000,0x0,0x3f703b37,0xbeb0eacb,0x3f42de29,0xbf26050a,0x3efafef7,0xbf5f20db,0x3ea2abb6,0xbffcbfc9,0xbe44b0b9,0xbf7b3bab,0xbf04f484,0xbf5ac450,0xbf485bca,0xbf1f599f,
0x3f800000,0x0,0x3f6f20b0,0xbeb6ccc3,0x3f3ebc1b,0xbf2ac082,0x3eea6681,0xbf6398ac,0x3e61bc2e,0xbffe70b0,0xbe80f8c0,0xbf77beb7,0xbf14b039,0xbf5064af,0xbf554aa4,0xbf0d9281,
0x3f800000,0x0,0x3f6dfcf2,0xbebca7af,0x3f3a7ca4,0xbf2f61a5,0x3ed97cb9,0xbf67c187,0x3dfb2b74,0xbfff84ab,0xbe9f1cdf,0xbf73530e,0xbf239da9,0xbf44e3f5,0xbf60a6cf,0xbef58035,
0x3f800000,0x0,0x3f6cd007,0xbec27b55,0x3f36206c,0xbf33e7bc,0x3ec8477c,0xbf6b99fb,0x3cc90e90,0xbffffb11,0xbebca7af,0xbf6dfcf2,0xbf31a81d,0xbf385216,0xbf6a5ad9,0xbece0bea,
0x3f800000,0x0,0x0,0x0,0x0,0x0,0x0,0x0,0x0,0x0,0x0,0x0,0x0,0x0,0x0,0x0,
0x0,0x0,0x0,0x0,0x0,0x0,0x0,0x0,0x0,0x0,0x0,0x0,0x0,0x0,0x0,0x0,
0x0,0x0,0x3e000000,0xbf20dff7,0x3ed0c429,0x0,0x3e000000,0x3e61f78b,0x3e0a8bd4,0x0,0x3e000000,0x3d5413cd,0x3d5df9ad,0x0,0x3e000000,0x3cf043ab,
0x0,0x0,0x3e000000,0x3ccbafaf,0xbd5df9ad,0x0,0x3e000000,0x3cf043ab,0xbe0a8bd4,0x0,0x3e000000,0x3d5413cd,0xbed0c429,0x0,0x3e000000,0x3e61f78b,
0x0,0x0,0x0,0x0,0x3f000000,0x0,0x0,0x3f000000,0x0,0x0,0x0,0x0,0x0,0x0,0x0,0x0,
0x0,0x0,0x0,0x0,0x0,0x0,0x0,0x0,0x0,0x0,0x0,0x0,0x3f000000,0x0,0x0,0xbf000000,
0x0,0x0,0x3e000000,0xbe3f90c7,0xbe8b7e3f,0x0,0x3e000000,0xbeb641af,0x3ea73d75,0x0,0x3e000000,0x3e9a827a,0x3da61ad1,0x0,0x3e000000,0x3dd906bd,
0x0,0x0,0x3e000000,0x3dab0dc1,0xbda61ad1,0x0,0x3e000000,0x3dd906bd,0xbea73d75,0x0,0x3e000000,0x3e9a827a,0x3e8b7e3f,0x0,0x3e000000,0xbeb641af,
0x0,0x0,0x0,0x0,0x0,0x0,0x0,0x0,0x3f000000,0x0,0x0,0x3f000000,0x0,0x0,0x0,0x0,
0x0,0x0,0x0,0x0,0x0,0x0,0x0,0x0,0x3f000000,0x0,0x0,0xbf000000,0x0,0x0,0x0,0x0,
0x0,0x0,0x3e000000,0xbdab0dc1,0xbda61ad1,0x0,0x3e000000,0xbdd906bd,0xbea73d75,0x0,0x3e000000,0xbe9a827a,0x3e8b7e3f,0x0,0x3e000000,0x3eb641af,
0x0,0x0,0x3e000000,0x3e3f90c7,0xbe8b7e3f,0x0,0x3e000000,0x3eb641af,0x3ea73d75,0x0,0x3e000000,0xbe9a827a,0x3da61ad1,0x0,0x3e000000,0xbdd906bd,
0x0,0x0,0x0,0x0,0x0,0x0,0x0,0x0,0x0,0x0,0x0,0x0,0x3f000000,0x0,0x0,0x3f000000,
0x0,0x0,0x0,0x0,0x3f000000,0x0,0x0,0xbf000000,0x0,0x0,0x0,0x0,0x0,0x0,0x0,0x0,
0x0,0x0,0x3e000000,0xbccbafaf,0xbd5df9ad,0x0,0x3e000000,0xbcf043ab,0xbe0a8bd4,0x0,0x3e000000,0xbd5413cd,0xbed0c429,0x0,0x3e000000,0xbe61f78b,
0x0,0x0,0x3e000000,0x3f20dff7,0x3ed0c429,0x0,0x3e000000,0xbe61f78b,0x3e0a8bd4,0x0,0x3e000000,0xbd5413cd,0x3d5df9ad,0x0,0x3e000000,0xbcf043ab,
};

struct Params {
    const __nv_bfloat16 *wr, *wi, *lre, *lim, *ldt, *dsk;
    float* out;
};

struct cf { float x, y; };
#define YIELD() asm volatile("pmevent 1;")
#define YS 14
#define YIELD_S1() do { if (YS & 1) YIELD(); } while (0)
#define YIELD_S2() do { if (YS & 2) YIELD(); } while (0)
#define YIELD_S3() do { if (YS & 4) YIELD(); } while (0)
__device__ __forceinline__ uint32_t smem_u32(const void* p) { return (uint32_t)__cvta_generic_to_shared(p); }
__device__ __forceinline__ void mbar_init(uint32_t a, uint32_t c) { asm volatile("mbarrier.init.shared::cta.b64 [%0], %1;" ::"r"(a), "r"(c) : "memory"); }
__device__ __forceinline__ void mbar_expect_tx(uint32_t a, uint32_t b) { asm volatile("mbarrier.arrive.expect_tx.shared::cta.b64 _, [%0], %1;" ::"r"(a), "r"(b) : "memory"); }
__device__ __forceinline__ void mbar_arrive(uint32_t a) { asm volatile("mbarrier.arrive.shared::cta.b64 _, [%0];" ::"r"(a) : "memory"); }
__device__ __forceinline__ void warp_arrive(uint32_t a) {
    __syncwarp();
    asm volatile("{.reg .pred p; elect.sync _|p, 0xffffffff; @p mbarrier.arrive.shared::cta.b64 _, [%0];}" ::"r"(a) : "memory");
}
__device__ __forceinline__ uint32_t mbar_try(uint32_t a, uint32_t ph) {
    uint32_t ok;
    asm volatile("{.reg .pred p; mbarrier.try_wait.parity.shared::cta.b64 p, [%1], %2; selp.u32 %0, 1, 0, p;}" : "=r"(ok) : "r"(a), "r"(ph) : "memory");
    return ok;
}
__device__ __forceinline__ void mbar_wait(uint32_t a, uint32_t ph) {
    uint32_t ok, n = 0;
    do { ok = mbar_try(a, ph); } while (!ok && ++n < SPIN_LIMIT);
}
__device__ __forceinline__ void mbar_wait_fast(uint32_t a, uint32_t ph) { if (!mbar_try(a, ph)) mbar_wait(a, ph); }
__device__ __forceinline__ unsigned ld_rlx(const unsigned* p) { unsigned v; asm volatile("ld.relaxed.gpu.global.u32 %0, [%1];" : "=r"(v) : "l"(p) : "memory"); return v; }
__device__ __forceinline__ void wait_cnt(const unsigned* p, unsigned target) {
    unsigned n = 0;
    while ((int)(ld_rlx(p) - target) < 0 && ++n < SPIN_LIMIT) __nanosleep(20);
}
__device__ __forceinline__ void red_hint(unsigned* p) { asm volatile("red.relaxed.gpu.global.add.u32 [%0], 1;" ::"l"(p) : "memory"); }
__device__ __forceinline__ void fence_async() { asm volatile("fence.proxy.async.global;" ::: "memory"); }
__device__ __forceinline__ void fence_async_sm() { asm volatile("fence.proxy.async.shared::cta;" ::: "memory"); }
#define bar_sync(id, n) asm volatile("bar.sync %0, %1;" ::"n"(id), "n"(n) : "memory")
#define bar_arrive(id, n) asm volatile("bar.arrive %0, %1;" ::"n"(id), "n"(n) : "memory")
__device__ __forceinline__ bool elect_one() {
    uint32_t r;
    asm volatile("{.reg .pred p; elect.sync _|p, 0xffffffff; selp.u32 %0, 1, 0, p;}" : "=r"(r));
    return r != 0;
}

__device__ __forceinline__ void tma2d(uint32_t dst, const CUtensorMap* m, int c0, int c1, uint32_t bar) {
    asm volatile("cp.async.bulk.tensor.2d.shared::cluster.global.mbarrier::complete_tx::bytes [%0], [%1, {%3,%4}], [%2];" ::"r"(dst), "l"(m), "r"(bar), "r"(c0), "r"(c1) : "memory");
}
__device__ __forceinline__ void tma3d(uint32_t dst, const CUtensorMap* m, int c0, int c1, int c2, uint32_t bar) {
    asm volatile("cp.async.bulk.tensor.3d.shared::cluster.global.mbarrier::complete_tx::bytes [%0], [%1, {%3,%4,%5}], [%2];" ::"r"(dst), "l"(m), "r"(bar), "r"(c0), "r"(c1), "r"(c2) : "memory");
}
__device__ __forceinline__ void tma2d_mc(uint32_t dst, const CUtensorMap* m, int c0, int c1, uint32_t bar) {
    asm volatile("cp.async.bulk.tensor.2d.shared::cluster.global.mbarrier::complete_tx::bytes.multicast::cluster [%0], [%1, {%3,%4}], [%2], %5;" ::"r"(dst), "l"(m), "r"(bar), "r"(c0), "r"(c1), "h"((uint16_t)3) : "memory");
}
__device__ __forceinline__ void tma4d_mc(uint32_t dst, const CUtensorMap* m, int c0, int c1, int c2, int c3, uint32_t bar) {
    asm volatile("cp.async.bulk.tensor.4d.shared::cluster.global.mbarrier::complete_tx::bytes.multicast::cluster [%0], [%1, {%3,%4,%5,%6}], [%2], %7;" ::"r"(dst), "l"(m), "r"(bar), "r"(c0), "r"(c1), "r"(c2), "r"(c3), "h"((uint16_t)3) : "memory");
}
__device__ __forceinline__ void tma4d(uint32_t dst, const CUtensorMap* m, int c0, int c1, int c2, int c3, uint32_t bar) {
    asm volatile("cp.async.bulk.tensor.4d.shared::cluster.global.mbarrier::complete_tx::bytes [%0], [%1, {%3,%4,%5,%6}], [%2];" ::"r"(dst), "l"(m), "r"(bar), "r"(c0), "r"(c1), "r"(c2), "r"(c3) : "memory");
}
__device__ __forceinline__ void tma2d_st(const CUtensorMap* m, int c0, int c1, uint32_t src) {
    asm volatile("cp.async.bulk.tensor.2d.global.shared::cta.bulk_group [%0, {%2,%3}], [%1];" ::"l"(m), "r"(src), "r"(c0), "r"(c1) : "memory");
}
__device__ __forceinline__ void tma3d_st(const CUtensorMap* m, int c0, int c1, int c2, uint32_t src) {
    asm volatile("cp.async.bulk.tensor.3d.global.shared::cta.bulk_group [%0, {%2,%3,%4}], [%1];" ::"l"(m), "r"(src), "r"(c0), "r"(c1), "r"(c2) : "memory");
}
__device__ __forceinline__ void tma5d(uint32_t dst, const CUtensorMap* m, int c0, int c1, int c2, int c3, int c4, uint32_t bar) {
    asm volatile("cp.async.bulk.tensor.5d.shared::cluster.global.mbarrier::complete_tx::bytes [%0], [%1, {%3,%4,%5,%6,%7}], [%2];" ::"r"(dst), "l"(m), "r"(bar), "r"(c0), "r"(c1), "r"(c2), "r"(c3), "r"(c4) : "memory");
}
__device__ __forceinline__ void tma5d_mc(uint32_t dst, const CUtensorMap* m, int c0, int c1, int c2, int c3, int c4, uint32_t bar) {
    asm volatile("cp.async.bulk.tensor.5d.shared::cluster.global.mbarrier::complete_tx::bytes.multicast::cluster [%0], [%1, {%3,%4,%5,%6,%7}], [%2], %8;" ::"r"(dst), "l"(m), "r"(bar), "r"(c0), "r"(c1), "r"(c2), "r"(c3), "r"(c4), "h"((uint16_t)3) : "memory");
}
__device__ __forceinline__ void bulk_pf(const void* src, uint32_t n) { asm volatile("cp.async.bulk.prefetch.L2.global [%0], %1;" ::"l"(src), "r"(n) : "memory"); }
__device__ __forceinline__ void tma4d_pf(const CUtensorMap* m, int c0, int c1, int c2, int c3) {
    asm volatile("cp.async.bulk.prefetch.tensor.4d.L2.global [%0, {%1,%2,%3,%4}];" ::"l"(m), "r"(c0), "r"(c1), "r"(c2), "r"(c3) : "memory");
}
__device__ __forceinline__ void tma5d_pf(const CUtensorMap* m, int c0, int c1, int c2, int c3, int c4) {
    asm volatile("cp.async.bulk.prefetch.tensor.5d.L2.global [%0, {%1,%2,%3,%4,%5}];" ::"l"(m), "r"(c0), "r"(c1), "r"(c2), "r"(c3), "r"(c4) : "memory");
}
__device__ __forceinline__ void bulk_ld(uint32_t dst, const void* src, uint32_t n, uint32_t bar) {
    asm volatile("cp.async.bulk.shared::cluster.global.mbarrier::complete_tx::bytes [%0], [%1], %2, [%3];" ::"r"(dst), "l"(src), "r"(n), "r"(bar) : "memory");
}
__device__ __forceinline__ void bulk_st(void* dst, uint32_t src, uint32_t n) {
    asm volatile("cp.async.bulk.global.shared::cta.bulk_group [%0], [%1], %2;" ::"l"(dst), "r"(src), "r"(n) : "memory");
}
__device__ __forceinline__ void bulk_commit() { asm volatile("cp.async.bulk.commit_group;" ::: "memory"); }
__device__ __forceinline__ void bulk_wait_read() { asm volatile("cp.async.bulk.wait_group.read 0;" ::: "memory"); }
__device__ __forceinline__ void bulk_wait_all() { asm volatile("cp.async.bulk.wait_group 0;" ::: "memory"); }
__device__ __forceinline__ void stsm4(uint32_t a, uint32_t r0, uint32_t r1, uint32_t r2, uint32_t r3) {
    asm volatile("stmatrix.sync.aligned.m8n8.x4.shared.b16 [%0], {%1,%2,%3,%4};" ::"r"(a), "r"(r0), "r"(r1), "r"(r2), "r"(r3) : "memory");
}
__device__ __forceinline__ void sts128(uint32_t a, uint32_t r0, uint32_t r1, uint32_t r2, uint32_t r3) {
    asm volatile("st.shared.v4.b32 [%0], {%1,%2,%3,%4};" ::"r"(a), "r"(r0), "r"(r1), "r"(r2), "r"(r3) : "memory");
}
__device__ __forceinline__ void lds128f(uint32_t a, float& x, float& y, float& z, float& u) { asm volatile("ld.shared.v4.f32 {%0,%1,%2,%3}, [%4];" : "=f"(x), "=f"(y), "=f"(z), "=f"(u) : "r"(a) : "memory"); }
__device__ __forceinline__ cf lds_cf(uint32_t a) { cf v; asm volatile("ld.shared.v2.f32 {%0,%1}, [%2];" : "=f"(v.x), "=f"(v.y) : "r"(a) : "memory"); return v; }
__device__ __forceinline__ void stg128(const void* a, uint32_t r0, uint32_t r1, uint32_t r2, uint32_t r3) {
    asm volatile("st.global.v4.b32 [%0], {%1,%2,%3,%4};" ::"l"(a), "r"(r0), "r"(r1), "r"(r2), "r"(r3) : "memory");
}
__device__ __forceinline__ int fresh_lane() { int v; asm volatile("mov.u32 %0, %%laneid;" : "=r"(v)); return v; }
__device__ __forceinline__ uint32_t opaque32(uint32_t v) { asm volatile("" : "+r"(v)); return v; }
__device__ __forceinline__ const uint8_t* padd(const void* base, uint32_t off) {
    uint64_t r;
    asm("{.reg .u32 l, h; mov.b64 {l, h}, %1; add.cc.u32 l, l, %2; addc.u32 h, h, 0; mov.b64 %0, {l, h};}" : "=l"(r) : "l"(base), "r"(off));
    return (const uint8_t*)r;
}
template <int N, int STRIDE> __device__ __forceinline__ void ldtab(uint32_t (&v)[4 * N], uint32_t off) {
    const uint8_t* a = padd(g_tab, off);
#pragma unroll
    for (int i = 0; i < N; i++)
        asm volatile("ld.global.nc.v4.b32 {%0,%1,%2,%3}, [%4];" : "=r"(v[4 * i]), "=r"(v[4 * i + 1]), "=r"(v[4 * i + 2]), "=r"(v[4 * i + 3]) : "l"(a + i * STRIDE));
}
template <int STRIDE> __device__ __forceinline__ void ldtab_cf(cf (&t)[8], uint32_t off) {
    uint32_t v[16];
    ldtab<4, STRIDE>(v, off);
#pragma unroll
    for (int i = 0; i < 8; i++) t[i] = {__uint_as_float(v[2 * i]), __uint_as_float(v[2 * i + 1])};
}
__device__ __forceinline__ uint32_t lds16(uint32_t a) { uint32_t v; asm volatile("ld.shared.u16 %0, [%1];" : "=r"(v) : "r"(a)); return v; }
__device__ __forceinline__ unsigned get_epoch(uint32_t bars) {
    mbar_wait(bars + B_EP, 0);
    unsigned e;
    asm volatile("ld.shared.u32 %0, [%1];" : "=r"(e) : "r"(bars + B_EPOCH) : "memory");
    return e;
}
__device__ __forceinline__ void sts64(uint32_t a, uint32_t x, uint32_t y) { asm volatile("st.shared.v2.b32 [%0], {%1,%2};" ::"r"(a), "r"(x), "r"(y) : "memory"); }
__device__ __forceinline__ uint32_t pk(float lo, float hi) { uint32_t r; asm("cvt.rn.bf16x2.f32 %0, %1, %2;" : "=r"(r) : "f"(hi), "f"(lo)); return r; }
__device__ __forceinline__ float bf2f(unsigned short v) { return __uint_as_float((uint32_t)v << 16); }

__device__ __forceinline__ uint64_t mkdesc(uint32_t addr, uint32_t lbo, uint32_t sbo, uint32_t swz) {
    return (uint64_t)((addr & 0x3FFFF) >> 4) | ((uint64_t)(lbo >> 4) << 16) | ((uint64_t)(sbo >> 4) << 32) | ((uint64_t)swz << 62);
}
__device__ __forceinline__ uint64_t opaque(uint64_t v) { asm volatile("" : "+l"(v)); return v; }
__device__ __forceinline__ void wg_fence() { asm volatile("wgmma.fence.sync.aligned;" ::: "memory"); }
__device__ __forceinline__ void wg_commit() { asm volatile("wgmma.commit_group.sync.aligned;" ::: "memory"); }
template <int N> __device__ __forceinline__ void wg_wait() { asm volatile("wgmma.wait_group.sync.aligned %0;" ::"n"(N) : "memory"); }
template <int N> __device__ __forceinline__ void pin(float (&d)[N]) {
#pragma unroll
    for (int i = 0; i < N; i++) asm volatile("" : "+f"(d[i])::"memory");
}
template <int N> __device__ __forceinline__ void pinu(uint32_t (&d)[N]) {
#pragma unroll
    for (int i = 0; i < N; i++) asm volatile("" : "+r"(d[i])::"memory");
}

#define R8(d, o) "+f"(d[o]), "+f"(d[o + 1]), "+f"(d[o + 2]), "+f"(d[o + 3]), "+f"(d[o + 4]), "+f"(d[o + 5]), "+f"(d[o + 6]), "+f"(d[o + 7])
#define L8 "%0,%1,%2,%3,%4,%5,%6,%7"
#define L32 L8 ",%8,%9,%10,%11,%12,%13,%14,%15,%16,%17,%18,%19,%20,%21,%22,%23,%24,%25,%26,%27,%28,%29,%30,%31"
#define L56 L32 ",%32,%33,%34,%35,%36,%37,%38,%39,%40,%41,%42,%43,%44,%45,%46,%47,%48,%49,%50,%51,%52,%53,%54,%55"
#define L64 L56 ",%56,%57,%58,%59,%60,%61,%62,%63"

template <int O, int TA, int TB, int N> __device__ __forceinline__ void mma128_ss(float (&d)[N], uint64_t da, uint64_t db, int sc) {
    asm volatile("{.reg .pred p; setp.ne.b32 p, %66, 0;\n"
                 "wgmma.mma_async.sync.aligned.m64n128k16.f32.bf16.bf16 {" L64 "}, %64, %65, p, 1, 1, %67, %68;}"
                 : R8(d, O), R8(d, O + 8), R8(d, O + 16), R8(d, O + 24), R8(d, O + 32), R8(d, O + 40), R8(d, O + 48), R8(d, O + 56)
                 : "l"(da), "l"(db), "r"(sc), "n"(TA), "n"(TB));
}
template <int O, int TB> __device__ __forceinline__ void mma128_rs(float (&d)[128], uint32_t a0, uint32_t a1, uint32_t a2, uint32_t a3, uint64_t db, int sc) {
    asm volatile("{.reg .pred p; setp.ne.b32 p, %69, 0;\n"
                 "wgmma.mma_async.sync.aligned.m64n128k16.f32.bf16.bf16 {" L64 "}, {%64,%65,%66,%67}, %68, p, 1, 1, %70;}"
                 : R8(d, O), R8(d, O + 8), R8(d, O + 16), R8(d, O + 24), R8(d, O + 32), R8(d, O + 40), R8(d, O + 48), R8(d, O + 56)
                 : "r"(a0), "r"(a1), "r"(a2), "r"(a3), "l"(db), "r"(sc), "n"(TB));
}
template <int TB> __device__ __forceinline__ void mma64_rs(float (&d)[32], uint32_t a0, uint32_t a1, uint32_t a2, uint32_t a3, uint64_t db, int sc) {
    asm volatile("{.reg .pred p; setp.ne.b32 p, %37, 0;\n"
                 "wgmma.mma_async.sync.aligned.m64n64k16.f32.bf16.bf16 {" L32 "}, {%32,%33,%34,%35}, %36, p, 1, 1, %38;}"
                 : R8(d, 0), R8(d, 8), R8(d, 16), R8(d, 24)
                 : "r"(a0), "r"(a1), "r"(a2), "r"(a3), "l"(db), "r"(sc), "n"(TB));
}
__device__ __forceinline__ void mma112_ss(float (&d)[64], uint64_t da, uint64_t db, int sc) {
    asm volatile("{.reg .pred p; setp.ne.b32 p, %58, 0;\n"
                 "wgmma.mma_async.sync.aligned.m64n112k16.f32.bf16.bf16 {" L56 "}, %56, %57, p, 1, 1, 0, 1;}"
                 : R8(d, 8), R8(d, 16), R8(d, 24), R8(d, 32), R8(d, 40), R8(d, 48), R8(d, 56)
                 : "l"(da), "l"(db), "r"(sc));
}
__device__ __forceinline__ void mma16_rs(float (&d)[64], uint32_t a0, uint32_t a1, uint32_t a2, uint32_t a3, uint64_t db, int sc) {
    asm volatile("{.reg .pred p; setp.ne.b32 p, %13, 0;\n"
                 "wgmma.mma_async.sync.aligned.m64n16k16.f32.bf16.bf16 {" L8 "}, {%8,%9,%10,%11}, %12, p, 1, 1, 1;}"
                 : R8(d, 0)
                 : "r"(a0), "r"(a1), "r"(a2), "r"(a3), "l"(db), "r"(sc));
}

__device__ __forceinline__ cf cmul(cf a, cf b) { return {fmaf(a.x, b.x, -a.y * b.y), fmaf(a.x, b.y, a.y * b.x)}; }
__device__ __forceinline__ cf cmulc(cf a, cf b) { return {fmaf(a.x, b.x, a.y * b.y), fmaf(a.y, b.x, -a.x * b.y)}; }
__device__ __forceinline__ cf cfma(cf a, cf b, cf c) { return {fmaf(a.x, b.x, fmaf(-a.y, b.y, c.x)), fmaf(a.x, b.y, fmaf(a.y, b.x, c.y))}; }
__device__ __forceinline__ cf csq(cf a) { return {fmaf(a.x, a.x, -a.y * a.y), (a.x * a.y) * 2.f}; }
__device__ __forceinline__ cf csel(int c, cf a, cf b) {
    cf r;
    asm("{.reg .pred p; setp.ne.s32 p, %2, 0; selp.f32 %0, %3, %5, p; selp.f32 %1, %4, %6, p;}" : "=f"(r.x), "=f"(r.y) : "r"(c), "f"(a.x), "f"(a.y), "f"(b.x), "f"(b.y));
    return r;
}
__device__ __forceinline__ cf cadd(cf a, cf b) { return {a.x + b.x, a.y + b.y}; }
__device__ __forceinline__ cf csub(cf a, cf b) { return {a.x - b.x, a.y - b.y}; }
__device__ __forceinline__ cf twice_minus(cf a, cf s) { return {fmaf(2.f, a.x, -s.x), fmaf(2.f, a.y, -s.y)}; }
__device__ __forceinline__ cf twid(int m, int M) {
    int r = ((m + M / 2) & (M - 1)) - M / 2;
    float s, c;
    __sincosf((float)r * (-6.283185307179586f / (float)M), &s, &c);
    return {c, s};
}
struct c2 { cf a, b; };
#define YP1 3
#define YP2 0
#define YP3 0
template <int Y> __device__ __forceinline__ void fin(c2& u) { if (Y & 1) asm volatile("pmevent 1;" : "+f"(u.a.x), "+f"(u.a.y), "+f"(u.b.x), "+f"(u.b.y)); }
template <int Y> __device__ __forceinline__ void fin(c2& u, c2& v) {
    if (Y & 2) asm volatile("pmevent 1;" : "+f"(u.a.x), "+f"(u.a.y), "+f"(u.b.x), "+f"(u.b.y), "+f"(v.a.x), "+f"(v.a.y), "+f"(v.b.x), "+f"(v.b.y));
}
__device__ __forceinline__ c2 mul2(c2 u, cf t) { return {cmul(u.a, t), cmul(u.b, t)}; }
__device__ __forceinline__ c2 mul2(c2 u, c2 t) { return {cmul(u.a, t.a), cmul(u.b, t.b)}; }
__device__ __forceinline__ c2 fma2(c2 u, cf t, c2 c) { return {cfma(u.a, t, c.a), cfma(u.b, t, c.b)}; }
__device__ __forceinline__ c2 fma2(c2 u, c2 t, c2 c) { return {cfma(u.a, t.a, c.a), cfma(u.b, t.b, c.b)}; }
__device__ __forceinline__ c2 twm2(c2 u, c2 s) { return {twice_minus(u.a, s.a), twice_minus(u.b, s.b)}; }
template <int Y> __device__ __forceinline__ void bfly(c2& u, c2& v) { const c2 t = u; u = {cadd(t.a, v.a), cadd(t.b, v.b)}; v = {csub(t.a, v.a), csub(t.b, v.b)}; fin<Y>(u, v); }
template <int Y> __device__ __forceinline__ void bfly_mi(c2& u, c2& v) {
    const c2 t = u, z = v;
    u = {{t.a.x + z.a.y, t.a.y - z.a.x}, {t.b.x + z.b.y, t.b.y - z.b.x}};
    v = {{t.a.x - z.a.y, t.a.y + z.a.x}, {t.b.x - z.b.y, t.b.y + z.b.x}};
    fin<Y>(u, v);
}
template <int Y> __device__ __forceinline__ void bfly_s(c2& u, c2& v) {
    const float s = 0.70710678118654752f;
    const c2 t = u, z = v;
    u = {{fmaf(s, z.a.x, t.a.x), fmaf(s, z.a.y, t.a.y)}, {fmaf(s, z.b.x, t.b.x), fmaf(s, z.b.y, t.b.y)}};
    v = {{fmaf(-s, z.a.x, t.a.x), fmaf(-s, z.a.y, t.a.y)}, {fmaf(-s, z.b.x, t.b.x), fmaf(-s, z.b.y, t.b.y)}};
    fin<Y>(u, v);
}
template <int Y, class T> __device__ __forceinline__ void bfly_tw(c2& u0, c2& v0, T t0, c2& u1, c2& v1, T t1) {
    v0 = fma2(v0, t0, u0); fin<Y>(v0);
    v1 = fma2(v1, t1, u1); fin<Y>(v1);
    const c2 a = twm2(u0, v0), b = twm2(u1, v1);
    u0 = v0; u1 = v1; v0 = a; v1 = b;
    fin<Y>(v0, v1);
}
template <bool TW, int Y> __device__ __forceinline__ void dft8(c2 (&v)[8], const cf (&tw)[8]) {
    if (TW) {
#pragma unroll
        for (int n = 1; n < 4; n++) { v[n] = mul2(v[n], tw[n]); fin<Y>(v[n]); }
        bfly_tw<Y>(v[0], v[4], tw[4], v[2], v[6], tw[6]);
        bfly_tw<Y>(v[1], v[5], tw[5], v[3], v[7], tw[7]);
    } else {
#pragma unroll
        for (int n = 0; n < 4; n++) bfly<Y>(v[n], v[n + 4]);
    }
    bfly<Y>(v[0], v[2]); bfly_mi<Y>(v[4], v[6]);
    bfly<Y>(v[1], v[3]); bfly_mi<Y>(v[5], v[7]);
    v[5] = {{v[5].a.x + v[5].a.y, v[5].a.y - v[5].a.x}, {v[5].b.x + v[5].b.y, v[5].b.y - v[5].b.x}};
    v[7] = {{v[7].a.y - v[7].a.x, -v[7].a.x - v[7].a.y}, {v[7].b.y - v[7].b.x, -v[7].b.x - v[7].b.y}};
    fin<Y>(v[5], v[7]);
    bfly<Y>(v[0], v[1]); bfly_s<Y>(v[4], v[5]); bfly_mi<Y>(v[2], v[3]); bfly_s<Y>(v[6], v[7]);
    const c2 t1 = v[1], t3 = v[3];
    v[1] = v[4]; v[4] = t1; v[3] = v[6]; v[6] = t3;
}

__device__ __forceinline__ void gather(uint64_t (&fv)[4], const uint8_t* a, int n) {
    asm volatile("{.reg .pred p0, p1, p2, p3;\n"
                 "setp.ge.s32 p0, %5, 0; setp.ge.s32 p1, %5, 4; setp.ge.s32 p2, %5, 8; setp.ge.s32 p3, %5, 12;\n"
                 "@p0 ld.relaxed.gpu.global.b64 %0, [%4]; @p1 ld.relaxed.gpu.global.b64 %1, [%4+-32768];\n"
                 "@p2 ld.relaxed.gpu.global.b64 %2, [%4+-65536]; @p3 ld.relaxed.gpu.global.b64 %3, [%4+-98304];}"
                 : "+l"(fv[0]), "+l"(fv[1]), "+l"(fv[2]), "+l"(fv[3]) : "l"(a), "r"(n) : "memory");
}
__device__ __forceinline__ cf as_cf(uint64_t v) { cf r; asm("mov.b64 {%0,%1}, %2;" : "=f"(r.x), "=f"(r.y) : "l"(v)); return r; }
template <int H> __device__ __forceinline__ void prescale(float (&u)[64], const float (&d)[128], cf gam) {
#pragma unroll
    for (int i = 0; i < 32; i += 2) {
        const int r = 2 * i + 2 * H;
        c2 v = mul2(c2{{d[r], -d[64 + r]}, {d[r + 1], -d[65 + r]}}, gam);
        if (YS & 2) asm volatile("pmevent 1;" : "+f"(v.a.x), "+f"(v.a.y), "+f"(v.b.x), "+f"(v.b.y));
        u[i] = v.a.x; u[32 + i] = v.a.y; u[i + 1] = v.b.x; u[33 + i] = v.b.y;
    }
}
__device__ __forceinline__ void scan2(const float (&u)[64], cf lam, cf st, const uint8_t* hptr, uint32_t hm, uint32_t hb, uint32_t& keep) {
    uint32_t hp[32];
#pragma unroll
    for (int jj = 0; jj < 4; jj++) {
        cf v[8];
#pragma unroll
        for (int i = 0; i < 8; i++) v[i] = st = cfma(lam, st, {u[8 * jj + i], u[32 + 8 * jj + i]});
        const int o = 8 * jj;
        hp[o] = pk(v[0].x, v[2].x); hp[o + 1] = pk(v[4].x, v[6].x); hp[o + 2] = pk(v[1].x, v[3].x); hp[o + 3] = pk(v[5].x, v[7].x);
        hp[o + 4] = pk(v[0].y, v[2].y); hp[o + 5] = pk(v[4].y, v[6].y); hp[o + 6] = pk(v[1].y, v[3].y); hp[o + 7] = pk(v[5].y, v[7].y);
        hp[o + jj] = (hp[o + jj] & hm) | hb;
        hp[o + 4 + jj] = (hp[o + 4 + jj] & hm) | hb;
        stg128(hptr + (jj >> 1) * 8192 + (jj & 1) * 512, hp[o], hp[o + 1], hp[o + 2], hp[o + 3]);
        stg128(hptr + 16384 + (jj >> 1) * 8192 + (jj & 1) * 512, hp[o + 4], hp[o + 5], hp[o + 6], hp[o + 7]);
        YIELD_S3();
        if (jj > 0) {
#pragma unroll
            for (int i = o - 8; i < o; i += 2) asm volatile("lop3.b32 %0, %0, %1, %2, 0x80;" : "+r"(keep) : "r"(hp[i]), "r"(hp[i + 1]));
        }
    }
}

__device__ __forceinline__ int pos_of(int n) { return (n & 24) + 4 * (n & 1) + ((n >> 1) & 3); }
__device__ __forceinline__ int unit_of(int role, int u, int& slot) {
    const int g = role & 7, w = (role >> 3) & 3, b = role >> 5;
    slot = role >= 128 ? g : (g ? 16 * g + w + 4 * b : 4 * w + b);
    return role >= 128 ? 32 * max(2 * g + u, 1) : (g ? g + 16 * w : ((w & 1) << 4) + ((w & 2) << 2)) + 64 * b + 256 * u;
}
template <int STRIDE> __device__ __forceinline__ bool tags_ok(uint32_t a, uint32_t ep) {
    uint32_t v[4], ok;
#pragma unroll
    for (int i = 0; i < 4; i++) {
        if (STRIDE || !i) asm volatile("ld.shared.u32 %0, [%1];" : "=r"(v[i]) : "r"(a + i * STRIDE) : "memory");
        else v[i] = v[0];
    }
    asm volatile("{.reg .pred p; .reg .b32 a, b; lop3.b32 a, %1, %2, %5, 0x7e; lop3.b32 b, %3, %4, %5, 0x7e; lop3.b32 a, a, b, 1, 0xa8;\n"
                 "setp.eq.u32 p, a, 0; vote.sync.all.pred p, p, -1; selp.u32 %0, 1, 0, p;}" : "=r"(ok) : "r"(v[0]), "r"(v[1]), "r"(v[2]), "r"(v[3]), "r"(ep));
    return ok;
}
__device__ __forceinline__ void load_w_rows(uint32_t dst, const CUtensorMap* mr, const CUtensorMap* mi, int kap, uint32_t bar) {
    mbar_expect_tx(bar, 16 * WPITCH);
#pragma unroll 1
    for (int i = 0; i < 2; i++, dst += 8 * WPITCH, kap = (512 - kap) & 511) {
        tma2d(dst, mr, (kap * 1026 >> 4) * 2, 0, bar);
        tma2d(dst + 4 * WPITCH, mi, (kap * 1026 >> 4) * 2, 0, bar);
    }
}
__device__ __forceinline__ void prefetch_w_rows(const CUtensorMap* mr, const CUtensorMap* mi, int kap) {
#pragma unroll 1
    for (int i = 0; i < 2; i++, kap = (512 - kap) & 511) {
        asm volatile("cp.async.bulk.prefetch.tensor.2d.L2.global [%0, {%1,%2}];" ::"l"(mr), "r"((kap * 1026 >> 4) * 2), "r"(0) : "memory");
        asm volatile("cp.async.bulk.prefetch.tensor.2d.L2.global [%0, {%1,%2}];" ::"l"(mi), "r"((kap * 1026 >> 4) * 2), "r"(0) : "memory");
    }
}
__device__ __forceinline__ void store_v(const uint32_t (&vo)[32], const uint8_t* vp, int k, bool p) {
    asm volatile("{.reg .pred p; setp.ne.u32 p, %3, 0; @p st.global.v2.b32 [%0], {%1,%2};}" ::"l"(vp + (k >> 2) * (1 << 20) + ((k >> 1) & 1) * 8192 + (k & 1) * (4 * 32768)), "r"(vo[2 * k]), "r"(vo[2 * k + 1]), "r"((int)p) : "memory");
}
__device__ __forceinline__ void hint_v(unsigned* cnt, int on) { asm volatile("{.reg .pred p; setp.ne.and.u32 p, %1, 0, p0; @p red.relaxed.gpu.global.add.u32 [%0], 1;}" ::"l"(cnt), "r"(on) : "memory"); }
#define SB0 1024
__device__ __forceinline__ uint64_t ring_desc(uint32_t sb, uint32_t off, uint32_t lbo, uint32_t swz) {
    uint64_t d;
    asm volatile("{.reg .b32 z; shr.u32 z, %1, 28; mov.b64 %0, {z, z}; add.u64 %0, %0, %2;}" : "=l"(d) : "r"(sb), "l"(mkdesc(SB0 + off, lbo, 1024, swz)));
    return d;
}
struct Ring {
    uint32_t full, rel;
    uint32_t n;
    bool sig;
};
__device__ __forceinline__ void ring_release(const Ring& r, uint32_t o) {
    if (r.sig) asm volatile("mbarrier.arrive.shared::cluster.b64 _, [%0];" ::"r"(r.rel + o) : "memory");
}
__device__ __forceinline__ void peek(uint32_t a, uint32_t ph) { asm volatile("mbarrier.test_wait.parity.shared::cta.b64 pk, [%0], %1;" ::"r"(a), "r"(ph) : "memory"); }
__device__ __forceinline__ void peek_wait(uint32_t a, uint32_t ph, uint32_t& n) {
    asm volatile("{@pk bra DONE;\n"
                 "LOOP: mbarrier.try_wait.parity.shared::cta.b64 pk, [%1], %2; add.u32 %0, %0, 1; setp.gt.or.u32 pk, %0, %3, pk; @!pk bra LOOP;\n"
                 "DONE: }" : "+r"(n) : "r"(a), "r"(ph), "n"(SPIN_LIMIT) : "memory");
}
#define SL(k) ((k) % NST)
#define PH(k) (((k) / NST) & 1)
#define HANDPOS 5
#define H64 "%64,%65,%66,%67,%68,%69,%70,%71,%72,%73,%74,%75,%76,%77,%78,%79,%80,%81,%82,%83,%84,%85,%86,%87,%88,%89,%90,%91,%92,%93,%94,%95," \
            "%96,%97,%98,%99,%100,%101,%102,%103,%104,%105,%106,%107,%108,%109,%110,%111,%112,%113,%114,%115,%116,%117,%118,%119,%120,%121,%122,%123,%124,%125,%126,%127"
#define WG_MMA "wgmma.mma_async.sync.aligned.m64n128k16.f32.bf16.bf16 "
#define DESC_B(S, j) "mov.b64 {t, hb}, %130; mov.b64 db, {%137 + 2048 * " #S " + 2 * " #j ", hb};\n"
#define MMA_LO(S, j, p) "add.u64 da, %129, 2048 * " #S " + %136 * " #j ";" DESC_B(S, j) WG_MMA "{" L64 "}, da, db, " #p ", 1, 1, %138, 0;\n"
#define MMA_HI(S, j, p) "add.u64 da, %129, 2048 * " #S " + 512 + %136 * " #j ";\n" WG_MMA "{" H64 "}, da, db, " #p ", 1, 1, %138, 0;\n"
#define X3(X)
#define X4(X)
#define X5(X) X
#define STEP(S, P, N, ph, pa, pr, X, Y) \
    "wgmma.fence.sync.aligned;\n" MMA_LO(S, 0, pa) MMA_HI(S, 0, pa) \
    "wgmma.commit_group.sync.aligned; wgmma.wait_group.sync.aligned 1; @" #pr " mbarrier.arrive.shared::cluster.b64 _, [%132 + 8 * " #P "];\n" MMA_LO(S, 1, 1) \
    "mbarrier.test_wait.parity.shared::cta.b64 pk, [%131 + 8 * " #N "], " #ph ";\n" X3(X) MMA_HI(S, 1, 1) X4(X) MMA_LO(S, 2, 1) X5(X) MMA_HI(S, 2, 1) MMA_LO(S, 3, 1) MMA_HI(S, 3, 1) \
    "wgmma.commit_group.sync.aligned;\n" P4A Y "@pk bra GO" #S ";\n" \
    "WAIT" #S ": mbarrier.try_wait.parity.shared::cta.b64 pk, [%131 + 8 * " #N "], " #ph "; add.u32 %128, %128, 1; setp.gt.or.u32 pk, %128, %139, pk; @!pk bra WAIT" #S ";\n" \
    "GO" #S ":\n" P4B
#define P4A
#define P4B
#define P4I
#define P4O
#define STEP_ARGS(TA) \
    : R8(d, 0), R8(d, 8), R8(d, 16), R8(d, 24), R8(d, 32), R8(d, 40), R8(d, 48), R8(d, 56), \
      R8(d, 64), R8(d, 72), R8(d, 80), R8(d, 88), R8(d, 96), R8(d, 104), R8(d, 112), R8(d, 120), "+r"(r.n) \
    : "l"(ha), "l"(hb), "r"(r.full), "r"(r.rel), "r"((uint32_t)r.sig), "r"(wg), \
      "n"(SB0 / 16 + (TA ? 32 << 16 : 1 << 16)), "n"(TA ? 128 : 2), "n"(SB0 / 16 + 1024 + (1 << 16)), "n"(TA), "n"(SPIN_LIMIT) P4O \
    : "memory"
#define STEP_REGS "{.reg .b32 k, t, ph, hb; .reg .b64 da, db; .reg .pred ps, pl, pa, pr;\n" P4I "setp.ne.u32 ps, %133, 0;\n"
#define FIRST_WAIT "FIRST: mbarrier.try_wait.parity.shared::cta.b64 pk, [t], ph; @pk bra START; add.u32 %128, %128, 1; setp.le.u32 pk, %128, %139; @pk bra FIRST; START:\n"
__device__ __forceinline__ void gemm1(float (&d)[128], Ring& r, uint64_t ha, uint64_t hb, int wg) {
    asm volatile(STEP_REGS "mul.lo.u32 k, %134, 15; mov.b32 ph, %134; setp.ne.u32 pl, k, 0; mad.lo.u32 t, %134, 8, %131;\n"
                 "pmevent 1; @pl bar.sync 1, 256;\n" FIRST_WAIT "@pl bra ONE;\n"
                 "LOOP: setp.ne.u32 pa, k, 0; and.pred pr, pa, ps; setp.eq.u32 pl, k, 15;\n"
                 STEP(0, 4, 1, ph, pa, pr, "@pl bar.arrive 1, 256;\n", "@pl bra END;\n")
                 "ONE: setp.ne.u32 pa, k, 15; and.pred pr, pa, ps; setp.eq.u32 pl, k, 30;\n"
                 STEP(1, 0, 2, ph, pa, pr, "@pl bar.arrive 2, 256;\n", "@pl bra END;\n")
                 STEP(2, 1, 3, ph, 1, ps, "", "") STEP(3, 2, 4, ph, 1, ps, "", "") "xor.b32 ph, ph, 1; add.u32 k, k, 5;\n" STEP(4, 3, 0, ph, 1, ps, "", "")
                 "bra LOOP;\n"
                 "END:\n" P4B "}" STEP_ARGS(0));
}
__device__ __forceinline__ void gemm2(float (&d)[128], Ring& r, uint64_t ha, uint64_t hb, int wg) {
    asm volatile(STEP_REGS "mov.b32 k, 0; mov.b32 ph, 0; add.u32 t, %131, 16;\n"
                 "pmevent 1; bar.sync 2, 256;\n" FIRST_WAIT
                 "LOOP: setp.ne.u32 pa, k, 0; and.pred pr, pa, ps; setp.eq.u32 pl, k, 5;\n"
                 STEP(2, 1, 3, ph, pa, pr, "", "") STEP(3, 2, 4, ph, 1, ps, "", "") "xor.b32 ph, ph, 1; add.u32 k, k, 1;\n" STEP(4, 3, 0, ph, 1, ps, "", "")
                 "@pl bra END;\n" STEP(0, 4, 1, ph, 1, ps, "", "") STEP(1, 0, 2, ph, 1, ps, "", "")
                 "bra LOOP;\n"
                 "END: }" STEP_ARGS(1));
}
template <int O, int K, int J> __device__ __forceinline__ void mma_h(float (&y)[128], uint64_t a, uint64_t b) { mma128_ss<O, 1, 0>(y, a + SL(K) * 2048 + O * 8 + 128 * J, b + SL(K) * 2048 + 2 * J, 1); }
template <int O, int K> __device__ __forceinline__ void half_step(float (&y)[128], uint64_t a, uint64_t b) { mma_h<O, K, 0>(y, a, b); mma_h<O, K, 1>(y, a, b); mma_h<O, K, 2>(y, a, b); mma_h<O, K, 3>(y, a, b); }
template <int R, int U> __device__ __forceinline__ void out_piece(float (&y)[128], const uint32_t (&dd)[16], uint32_t x0, uint32_t x1, float* op) {
    const int i = 64 * (R >> 1) + 8 * U + 2 * (R & 1);
    asm("mul.rn.bf16x2 %0, %0, %1;" : "+r"(x0) : "r"(dd[2 * U]));
    asm("mul.rn.bf16x2 %0, %0, %1;" : "+r"(x1) : "r"(dd[2 * U + 1]));
    asm volatile("st.global.v4.f32 [%0], {%1,%2,%3,%4};" ::"l"(op + (32 * (R & 1) + 16 * (R >> 1)) * 2048 + 16 * U),
                 "f"(y[i] + __uint_as_float(x0 << 16)), "f"(y[i + 1] + __uint_as_float(x0 & 0xffff0000u)),
                 "f"(y[i + 4] + __uint_as_float(x1 << 16)), "f"(y[i + 5] + __uint_as_float(x1 & 0xffff0000u)) : "memory");
}
template <int R, int U0> __device__ __forceinline__ void load_x4(uint32_t (&xx)[8], uint32_t xa) {
#pragma unroll
    for (int u = 0; u < 4; u++)
        asm volatile("ld.shared.v2.b32 {%0,%1}, [%2];" : "=r"(xx[2 * u]), "=r"(xx[2 * u + 1]) : "r"((xa ^ (u << 5)) + (3 - R) * 8192 + U0 * 1024) : "memory");
}
__device__ __forceinline__ Ring ring_at(uint32_t sb, int k) {
    Ring r;
    r.n = 0;
    r.full = sb + OFF_BAR + B_FULL;
    asm("mapa.shared::cluster.u32 %0, %1, %2;" : "=r"(r.rel) : "r"(sb + OFF_BAR + B_EMPTY), "r"((threadIdx.x >> 5) & 1));
    r.sig = __shfl_sync(~0u, threadIdx.x & 95, threadIdx.x) == 0;
    return r;
}

template <bool BY_SM> __global__ void __cluster_dims__(2, 1, 1) __launch_bounds__(512, 1)
fused_kernel(const __grid_constant__ CUtensorMap tmX, const __grid_constant__ CUtensorMap tmBre, const __grid_constant__ CUtensorMap tmBim,
             const __grid_constant__ CUtensorMap tmCre, const __grid_constant__ CUtensorMap tmCim, const __grid_constant__ CUtensorMap tmXd,
             const __grid_constant__ CUtensorMap tmUst,
             const __grid_constant__ CUtensorMap tmWr, const __grid_constant__ CUtensorMap tmWi, const __grid_constant__ CUtensorMap tmXa,
             const Params p) {
    extern __shared__ __align__(1024) uint8_t smraw[];
    asm volatile(".reg .pred pk, p0;");
    const int tid = TIDMAP, rank = blockIdx.x & 1;
    const uint32_t wi = __shfl_sync(~0u, smem_u32(smraw) + (tid >> 5), 0), sb = wi & ~15u, bars = sb + OFF_BAR;
    const int wg = (wi >> 2) & 3, w = wi & 3, lane = tid & 31, g = lane >> 2, q = lane & 3;
    if (wg != 3) asm volatile("barrier.cluster.arrive.relaxed.aligned; barrier.cluster.wait.aligned;" ::: "memory");
    else asm volatile("prefetch.tensormap [%0];" ::"l"(w == 0 ? &tmX : w == 1 ? &tmBre : &tmBim) : "memory");
    int role;
    {
        uint32_t T = blockIdx.x;
        if (BY_SM) asm("mov.u32 %0, %%smid;" : "=r"(T));
        T >>= 1;
        const uint32_t a = ((T - 32) * 37) >> 8;
        asm("{.reg .pred p; setp.lt.u32 p, %1, 62; selp.u32 %0, 4, -58, p; add.u32 %0, %0, %1;\n"
            "setp.lt.u32 p, %1, 60; selp.u32 %0, %2, %0, p; setp.lt.u32 p, %1, 32; selp.u32 %0, %3, %0, p;}"
            : "=&r"(role) : "r"(T), "r"(8 * (T - 31 - 7 * a) + 4 + a), "r"(8 * (T & 7) + (T >> 3)));
        role = 2 * role + rank;
    }
    const bool spare = role >= 128;
    const int tc = ((role >> 3) & 14) + rank, cb = (role >> 1) & 7;
    const int fb = role >> 5, fcb = role & 31, fpos = pos_of(fcb);
    const int nu = role == 128 ? 1 : (fcb || !role ? 2 : 0);

    if (wg == 3) {
        if (elect_one()) {
            const uint32_t b = bars + w * 8;
            STAMP5(57);
            mbar_init(b, 1);
            if (w < 2 && !spare) {
                mbar_expect_tx(b, 32768);
                tma5d(sb + w * 32768 + 16384, &tmX, w * 64, 0, 0, 0, tc, b);
                if (w == 0) { tma4d(sb, &tmBre, 0, 0, 0, cb * 4, b); tma4d(sb + 8192, &tmBim, 0, 0, 0, cb * 4, b); }
                STAMP5(58);
            }
#pragma unroll
            for (int o = 32; o < B_EPOCH; o += 32) mbar_init(b + o, o < B_EMPTY ? 1 : (o < B_STG ? 2 : (o < B_P3M ? 4 : 8)));
            asm volatile("fence.mbarrier_init.release.cluster;" ::: "memory");
        }
        __syncwarp();
        STAMP5(59);
        asm volatile("barrier.cluster.arrive.relaxed.aligned;" ::: "memory");
    }
    if (opaque32(wg) == 3) {
        asm volatile("setmaxnreg.dec.sync.aligned.u32 24;");
        asm volatile("barrier.cluster.wait.aligned;" ::: "memory");
        if (w == 0) {
            if (!spare && elect_one()) {
                STAMP(56);
#pragma unroll 1
                for (int k = 1; k < NST; k++) {
                    if (k >= 2) mbar_expect_tx(bars + B_FULL + k * 8, 32768);
                    tma4d_mc(sb + k * 32768 + rank * 8192, rank ? &tmBim : &tmBre, k * 64, 0, 0, cb * 4, bars + B_FULL + k * 8);
                    if (k >= 2) tma5d(sb + k * 32768 + 16384, &tmX, k * 64, 0, 0, 0, tc, bars + B_FULL + k * 8);
                }
#define RING_WAIT "mbarrier.try_wait.parity.shared::cta.b64 p, [fb + 256], ph; @p bra GO;\n" \
                  "WAIT: mbarrier.try_wait.parity.shared::cta.b64 p, [fb + 256], ph; add.u32 n, n, 1; setp.gt.or.u32 p, n, 32768, p; @!p bra WAIT;\nGO:\n"
#define RING_NEXT "pmevent 1; add.u32 o, o, 8; setp.eq.u32 p, o, 40; selp.u32 o, 0, o, p; @p xor.b32 ph, ph, 1; add.u32 fb, %1, o; shl.b32 t, o, 12; add.u32 da, %0, t;\n"
                asm volatile("{.reg .b32 o, k, kk, c2, da, db, fb, ph, n, t; .reg .pred p;\n"
                             "mov.b32 o, 0; mov.b32 k, 320; mov.b32 kk, 320; mov.b32 c2, 0; mov.b32 ph, 0; mov.b32 n, 0; mov.b32 fb, %1; mov.b32 da, %0; mov.b32 db, %2;\n"
                             "LOOP:\n" RING_WAIT
                             "cp.async.bulk.tensor.5d.shared::cluster.global.mbarrier::complete_tx::bytes [da], [%3, {kk,0,0,0,%5}], [fb];\n"
                             "cp.async.bulk.tensor.4d.shared::cluster.global.mbarrier::complete_tx::bytes.multicast::cluster [db], [%4, {kk,0,c2,%6}], [fb], %7;\n"
                             "mbarrier.arrive.expect_tx.shared::cta.b64 _, [fb], 32768;\n" RING_NEXT
                             "add.u32 db, %2, t; add.u32 k, k, 64; and.b32 kk, k, 1023; shr.u32 c2, k, 9; and.b32 c2, c2, 2; setp.ne.u32 p, k, 2048; @p bra LOOP;}"
                             ::"r"(sb + 16384), "r"(bars + B_FULL), "r"(sb + rank * 8192), "l"(&tmX), "l"(rank ? &tmBim : &tmBre), "r"(tc), "r"(cb * 4), "h"((uint16_t)3) : "memory");
                asm volatile("{.reg .b32 o, k, kk, da, db, fb, hb, ph, n, t; .reg .b64 m, src; .reg .pred p;\n"
                             "mov.b32 o, 16; mov.b32 k, 0; mov.b32 kk, 0; mov.b32 ph, 1; mov.b32 n, 0; add.u32 fb, %1, 16; add.u32 hb, %1, 72; add.u32 da, %0, 65536; add.u32 db, %2, 65536;\n"
                             "mov.b64 m, %3; mov.b64 src, %5;\n"
                             "GROUP: add.u32 t, %8, k;\n"
                             "OWN: mbarrier.try_wait.parity.shared::cta.b64 p, [t], 0; add.u32 n, n, 1; setp.gt.or.u32 p, n, 32768, p; @!p bra OWN;\n"
                             "LOOP:\n" RING_WAIT
                             "cp.async.bulk.shared::cluster.global.mbarrier::complete_tx::bytes [da], [src], 16384, [hb];\n"
                             "cp.async.bulk.tensor.5d.shared::cluster.global.mbarrier::complete_tx::bytes.multicast::cluster [db], [m, {kk,0,0,0,%6}], [fb], %7;\n"
                             "mbarrier.expect_tx.shared::cta.b64 [fb], 16384; mbarrier.arrive.expect_tx.shared::cta.b64 _, [hb], 16384;\n" RING_NEXT
                             "add.u32 db, %2, t; add.u64 src, src, 16384; sub.u64 m, %4, m; add.u32 k, k, 1; shl.b32 kk, k, 5; and.b32 kk, kk, 0x7c0;\n"
                             "and.b32 t, k, 1; mad.lo.u32 hb, t, 8, fb; add.u32 hb, hb, o; add.u32 hb, hb, 40;\n"
                             "and.b32 t, k, 7; setp.ne.u32 p, t, 0; @p bra LOOP; setp.ne.u32 p, k, 32; @p bra GROUP;}"
                             ::"r"(sb), "r"(bars + B_FULL), "r"(sb + 16384 + rank * 8192), "l"(&tmCre), "l"((uint64_t)&tmCre + (uint64_t)&tmCim),
                               "l"(g_H + (size_t)tc * 32 * 16384), "r"(cb * 8 + rank * 4), "h"((uint16_t)3), "r"(bars + B_HOWN) : "memory");
            }
        } else if (opaque32(w) == 1) {
            const unsigned ep = ld_rlx(g_epoch + role * 8) + 1;
            __syncwarp();
            if (elect_one()) {
                asm volatile("st.relaxed.gpu.global.u32 [%0], %1;" ::"l"(g_epoch + role * 8), "r"(ep) : "memory");
                asm volatile("st.shared.u32 [%0], %1;" ::"r"(bars + B_EPOCH), "r"(ep) : "memory");
                mbar_arrive(bars + B_EP);
            }
            int slot;
            const int kap = unit_of(role, 0, slot), kap1 = unit_of(role, 1, slot);
            uint32_t lph = 0;
            if (!spare) mbar_wait(bars + B_STGU, 0);
            STAMP(21);
            const int c0 = fb * 2048 + fpos * 64;
            if (elect_one()) {
                if (!spare) {
#pragma unroll 1
                    for (int r = 4; r < 8; r++) bulk_st(g_X + r * (32 * 16384) + c0 * 2, sb + OFF_P + r * 4096, 128);
                    tma2d_st(&tmUst, c0, 0, sb + OFF_P);
                    bulk_commit();
                    tma2d_st(&tmUst, c0, 64, sb + OFF_P + 8192);
                    bulk_commit();
                    if (UHINT == 1) asm volatile("cp.async.bulk.wait_group.read 1;" ::: "memory");
                    if (UHINT < 2) red_hint(g_cnt);
                }
                mbar_expect_tx(bars + B_FG, 8192);
                bulk_ld(sb + OFF_F, (const uint8_t*)g_tab + TAB_FG, 8192, bars + B_FG);
            }
            STAMP(40);
#pragma unroll 1
            for (int e = 0; e < 4; e++) {
                if (e >= 2) {
                    if (e == nu) {
                        mbar_wait(bars + B_WFREE, 0);
                        if (elect_one()) load_w_rows(sb + OFF_WD, &tmWr, &tmWi, kap1, bars + B_WD);
                    }
                    if (e - 2 < nu) mbar_wait(bars + B_STG, e & 1);
                    STAMPO(23, e - 2);
                    if (e == 3 && !spare && elect_one()) {
                        mbar_expect_tx(bars + B_FG, 8192);
                        bulk_ld(sb + OFF_F, (const uint8_t*)g_tab + TAB_G + fb * 8192, 8192, bars + B_FG);
                    }
                }
                const uint32_t tg = e < 2 ? lane * 128 + ((((lane >> 1) & 2) ^ (lane & 3)) << 4) + (lane >> 3) * 4 : lane * 64 + (lane & 8) * 4 + (lane & 2) * 8 + (lane & 4) * 2;
                if (spare) {
                    if (e == 1) {
                        wait_cnt(g_cnt, 128 * ep);
                        STAMP(42);
#pragma unroll 1
                        for (int n = 0; n < 4096; n++) {
                            if (elect_one()) {
                                mbar_expect_tx(bars + B_LD, 8 * 16384);
#pragma unroll 1
                                for (int r = 0; r < 8; r++) bulk_ld(sb + r * 16384, g_X + (size_t)r * (32 * 16384), 16384, bars + B_LD);
                            }
                            mbar_wait(bars + B_LD, n & 1);
                            bool ok = true;
#pragma unroll 1
                            for (int r = 0; r < 8; r++) ok &= tags_ok<4096>(sb + r * 16384 + tg, ep);
                            if (ok) break;
                        }
                        if (elect_one()) mbar_arrive(bars + B_RAW);
                    }
                } else {
                    const uint32_t dst = sb + OFF_P + (e & 1) * 16384;
                    wait_cnt(g_cnt + e * 32, 128 * ep);
                    STAMPO(41, e == 2 ? -12 : e);
#pragma unroll 1
                    for (int n = 0; n < 4096; n++) {
                        if (elect_one()) {
                            bulk_wait_read();
                            mbar_expect_tx(bars + B_LD, 16384);
                            bulk_ld(dst, g_X + (size_t)(e < 2 ? role + e * 128 : 254 + (fb * 32 + fpos) * 2 + e) * 16384, 16384, bars + B_LD);
                            if (U1POS <= 0 && e + n == 0) {
                                if (U1POS < 0 && nu) load_w_rows(sb + OFF_WD, &tmWr, &tmWi, kap, bars + B_WD);
                                tma2d_st(&tmUst, c0, 128, dst + 16384); tma2d_st(&tmUst, c0, 192, dst + 24576); bulk_commit();
                                if (U1POS == -2) { bulk_wait_read(); red_hint(g_cnt + 32); }
                            }
                        }
                        mbar_wait(bars + B_LD, lph);
                        if (!e) STAMP3(49);
                        lph ^= 1;
                        if (tags_ok<4096>(dst + tg, ep) & tags_ok<4096>(dst + tg + (e & 2) * 1024, ep) & tags_ok<0>(dst + (e == 3 ? (lane & 1) * 8192 + 32 : 0), ep)) break;
                    }
                    if (elect_one()) mbar_arrive(bars + B_IN + e * 8);
                }
                if (e < 2 && elect_one()) {
                    if (e) prefetch_w_rows(&tmWr, &tmWi, kap1);
                    else {
                        if (U1POS < 0 ? spare : nu) load_w_rows(sb + OFF_WD, &tmWr, &tmWi, kap, bars + B_WD);
                        if (!spare && U1POS != -2) {
                            if (U1POS > 0) { tma2d_st(&tmUst, c0, 128, sb + OFF_P + 16384); bulk_commit(); tma2d_st(&tmUst, c0, 192, sb + OFF_P + 24576); bulk_commit(); }
                            if (U1POS == 2) asm volatile("cp.async.bulk.wait_group.read 1;" ::: "memory"); else bulk_wait_read();
                            red_hint(g_cnt + 32);
                        }
                    }
                }
            }
            if (!spare) {
                mbar_wait(bars + B_HOWN + 8, 0);
#pragma unroll 1
                for (int r = 0; r < 4; r++) {
                    if (r == 3) mbar_wait(bars + B_P3M, 0);
                    if (elect_one()) {
                        if (r == 0) { mbar_expect_tx(bars + B_XD, 24576 + 256); mbar_expect_tx(bars + B_XD + 8, 8192); bulk_ld(sb + OFF_LAM, p.dsk + cb * 128, 256, bars + B_XD); }
                        tma4d(sb + OFF_F + (3 - r) * 8192, &tmXd, 0, tc * 128 + 32 * (r & 1) + 16 * (r >> 1), 0, cb * 2, bars + B_XD + (r == 3) * 8);
                    }
                    __nanosleep(PACE_X);
                }
            }
        } else {
            if (w == 2) {
                {
                    const int u = lane >> 4;
                    int slot;
                    const int r0 = unit_of(role, u, slot) + 512 * ((lane >> 1) & 3), r1 = (2048 - r0) & 2047, mir = (lane >> 3) & 1;
                    const unsigned short* wp = (const unsigned short*)((lane & 1) ? p.wi : p.wr);
                    const float a = bf2f(wp[r0 * 513 + mir * 512]), b = bf2f(wp[r1 * 513 + mir * 512]);
                    asm volatile("st.shared.f32 [%0], %1;" ::"r"(sb + OFF_WSP + u * 64 + (lane & 15) * 4), "f"(0.5f * ((lane & 1) ? (mir ? b - a : a - b) : a + b)) : "memory");
                }
                warp_arrive(bars + B_WSP);
            } else if (!spare) {
                if (XA_T0) __nanosleep(XA_T0);
#pragma unroll 1
                for (int i = 0; i < 8; i++) {
                    if (i >= XA_N0) __nanosleep(XA_PACE);
                    if (elect_one()) {
                        if (i == 0) mbar_expect_tx(bars + B_XIN, 32768);
                        tma3d(sb + OFF_F + i * 4096, &tmXa, fcb * 32, 0, 4 * i + fb, bars + B_XIN);
                    }
                }
            }
            if (!spare) {
                if (w == 2 && nu) {
                    int slot;
                    const int kap = unit_of(role, 0, slot);
                    mbar_wait(bars + WPFB, 0);
                    if (elect_one()) prefetch_w_rows(&tmWr, &tmWi, kap);
                }
                const unsigned ep = get_epoch(bars);
#define CNT_RETRY
#define CNT_ARG
                asm volatile("{.reg .b32 o, k, hb, fb, ca, m, ph, rph, n, t, v0, v1, v2, v3; .reg .b64 src; .reg .pred p, pe;\n"
                             "elect.sync _|pe, 0xffffffff; mov.b32 o, %0; shr.u32 k, %0, 3; sub.u32 k, k, 2; mov.b32 m, 0x107c0; mov.b32 rph, 0; mov.b32 n, 0;\n"
                             "bra NEXT;\n"
                             "LOOP: mbarrier.try_wait.parity.shared::cta.b64 p, [hb], ph; @p bra GO;\n"
                             "WAIT: mbarrier.try_wait.parity.shared::cta.b64 p, [hb], ph; add.u32 n, n, 1; setp.gt.or.u32 p, n, 32768, p; @!p bra WAIT;\n"
                             "GO: ld.shared.u32 v0, [ca]; ld.shared.u32 v1, [ca + 128]; ld.shared.u32 v2, [ca + 256]; ld.shared.u32 v3, [ca + 384];\n"
                             "lop3.b32 v0, v0, v1, %4, 0x7e; lop3.b32 v2, v2, v3, %4, 0x7e; lop3.b32 v0, v0, v2, 1, 0xa8; setp.eq.u32 p, v0, 0; vote.sync.all.pred p, p, -1; @p bra OK;\n"
                             CNT_RETRY "add.u32 n, n, 16; setp.gt.u32 p, n, 32768; @p bra OK;\n"
                             "shl.b32 t, o, 12; add.u32 t, t, %5; mad.wide.u32 src, k, 16384, %6;\n"
                             "@pe mbarrier.arrive.expect_tx.shared::cta.b64 _, [%7], 16384; @pe cp.async.bulk.shared::cluster.global.mbarrier::complete_tx::bytes [t], [src], 16384, [%7];\n"
                             "AGAIN: mbarrier.try_wait.parity.shared::cta.b64 p, [%7], rph; add.u32 n, n, 1; setp.gt.or.u32 p, n, 32768, p; @!p bra AGAIN;\n"
                             "xor.b32 rph, rph, 1; bra GO;\n"
                             "OK: @pe mbarrier.arrive.shared::cta.b64 _, [fb]; pmevent 1;\n"
                             "add.u32 o, o, 16; setp.ge.u32 p, o, 40; @p sub.u32 o, o, 40; add.u32 k, k, 2;\n"
                             "NEXT: shr.u32 m, m, 1; and.b32 ph, m, 1; add.u32 fb, %1, o; mad.lo.u32 hb, o, 2, %2; mad.lo.u32 ca, o, 4096, %3; setp.lt.u32 p, k, 32; @p bra LOOP;}"
                             ::"r"(8 * w), "r"(bars + B_FULL), "r"(bars + B_HL - 16 + w * 8), "r"(sb + (q >> 1) * 8192 + (q & 1) * 512 + g * 1040 + q * 4), "r"(ep),
                               "r"(sb), "l"(g_H + (size_t)tc * 32 * 16384), "r"(bars + B_HR - 16 + w * 8) CNT_ARG : "memory");
                if (w == 3) warp_arrive(bars + B_DONE);
            }
        }
    } else {
        STAMP(55);
        asm volatile("setmaxnreg.inc.sync.aligned.u32 152;");
        STAMP5(60);
        const int t7 = tid & 127, hf = wg - 1;
        const int mi = lane >> 3, gl = lane & 7;
        if (spare && wg != 2) {
            if (tid < 64) { const uint4 v = __ldg((const uint4*)((const uint8_t*)g_tab + TAB_PC) + tid); sts128(sb + OFF_LAM + tid * 16, v.x, v.y, v.z, v.w); }
            bar_sync(1, 256);
            mbar_wait(bars + B_RAW, 0);
            STAMP(0);
#pragma unroll 1
            for (int u = 0; u < nu; u++) {
                int slot;
                const int t = unit_of(role, u, slot) >> 5;
                const uint32_t off = (tid >> 2) * 128 + q * 16;
                float zr[16], zi[16];
#pragma unroll
                for (int k = 0; k < 16; k++) zr[k] = zi[k] = 0.f;
#pragma unroll 1
                for (int r = (t & 1) ? 0 : t >> 1; r < 8 - ((t & 1) ? 0 : (t >> 1) - 1); r += (t & 1) ? 1 : 8 - t) {
                    float4 c;
                    float a[8], b[8];
                    lds128f(sb + OFF_LAM + t * 128 + r * 16, c.x, c.y, c.z, c.w);
                    lds128f(sb + r * 16384 + off, a[0], a[1], a[2], a[3]);
                    lds128f(sb + r * 16384 + off + 64, b[0], b[1], b[2], b[3]);
                    lds128f(sb + r * 16384 + off + 8192, a[4], a[5], a[6], a[7]);
                    lds128f(sb + r * 16384 + off + 8192 + 64, b[4], b[5], b[6], b[7]);
#pragma unroll
                    for (int k = 0; k < 16; k++) {
                        const uint32_t ua = __float_as_uint(a[k >> 1]), ub = __float_as_uint(b[k >> 1]);
                        const float x = __uint_as_float((k & 1) ? ua & 0xffff0000u : ua << 16), y = __uint_as_float((k & 1) ? ub & 0xffff0000u : ub << 16);
                        zr[k] = fmaf(c.x, x, fmaf(c.z, y, zr[k]));
                        zi[k] = fmaf(c.y, x, fmaf(c.w, y, zi[k]));
                    }
                }
                const uint32_t dst = sb + OFF_P + u * 16384 + off;
#pragma unroll
                for (int k = 0; k < 16; k += 8) {
                    sts128(dst + k * 1024, pk(zr[k], zr[k + 1]), pk(zr[k + 2], zr[k + 3]), pk(zr[k + 4], zr[k + 5]), pk(zr[k + 6], zr[k + 7]));
                    sts128(dst + k * 1024 + 64, pk(zi[k], zi[k + 1]), pk(zi[k + 2], zi[k + 3]), pk(zi[k + 4], zi[k + 5]), pk(zi[k + 6], zi[k + 7]));
                }
                fence_async_sm();
                bar_sync(1, 256);
                if (tid == 0) mbar_arrive(bars + B_IN + u * 8);
                STAMPO(1, u);
            }
            return;
        }
        if (wg == 2 && !spare) {
            asm volatile("setmaxnreg.inc.sync.aligned.u32 176;");
            uint32_t f1[16];
            cf tw[8];
            if (TAB_T0) __nanosleep(TAB_T0);
            ldtab<4, 2048>(f1, TAB_F1 + t7 * 16);
            ldtab_cf<16>(tw, TAB_TW1 + (t7 >> 2) * 64);
            const uint32_t ep = get_epoch(bars);
            uint32_t a0 = sb + OFF_P + (8 * w + gl + 32 * (mi >> 1)) * 128 + (((((mi & 1) << 2) | (fpos & 3)) ^ gl) << 4);
            float acc[128];
            const uint64_t dx = opaque(mkdesc(sb + OFF_F, 4096, 512, 2));
            mbar_wait(bars + B_XIN, 0);
            STAMP(20);
            pinu(f1);
            wg_fence();
#pragma unroll
            for (int j = 0; j < 4; j++) {
                mma128_rs<0, 1>(acc, f1[4 * j], f1[4 * j + 1], f1[4 * j + 2], f1[4 * j + 3], dx + j * 64, j);
                mma128_rs<64, 1>(acc, f1[4 * j], f1[4 * j + 1], f1[4 * j + 2], f1[4 * j + 3], dx + 1024 + j * 64, j);
            }
            wg_commit();
            wg_wait<0>();
            pin(acc);
            pinu(f1);
#pragma unroll 1
            for (int h = 0;; h++) {
                const uint32_t tmask = 2 * q + h == fpos >> 2 ? ~1u : ~0u, tbit = ep & ~tmask;
#pragma unroll
                for (int cl = 0; cl < 2; cl++) {
                    c2 v[8];
#pragma unroll
                    for (int n = 0; n < 8; n++) {
                        const int i = 4 * (4 * n + cl);
                        v[n] = {{acc[i], acc[i + 2]}, {acc[i + 1], acc[i + 3]}};
                    }
                    dft8<true, YP1>(v, tw);
#pragma unroll
                    for (int r = 0; r < 8; r += 2) {
                        uint32_t o0 = pk(v[r].a.x, v[r].b.x), o1 = pk(v[r].a.y, v[r].b.y), o2 = pk(v[r + 1].a.x, v[r + 1].b.x), o3 = pk(v[r + 1].a.y, v[r + 1].b.y);
                        if (cl == 0) { o0 = (o0 & tmask) | tbit; o2 = (o2 & tmask) | tbit; }
                        stsm4((a0 ^ (cl << 4)) + r * 4096, o0, o1, o2, o3);
                    }
                }
                if (h) break;
                a0 ^= 32;
#pragma unroll
                for (int n = 0; n < 8; n++) {
                    asm volatile("mov.b32 %0, %8; mov.b32 %1, %9; mov.b32 %2, %10; mov.b32 %3, %11; mov.b32 %4, %12; mov.b32 %5, %13; mov.b32 %6, %14; mov.b32 %7, %15; pmevent 1;"
                                 : "=&f"(acc[16 * n]), "=&f"(acc[16 * n + 1]), "=&f"(acc[16 * n + 2]), "=&f"(acc[16 * n + 3]), "=&f"(acc[16 * n + 4]), "=&f"(acc[16 * n + 5]), "=&f"(acc[16 * n + 6]), "=&f"(acc[16 * n + 7])
                                 : "f"(acc[16 * n + 8]), "f"(acc[16 * n + 9]), "f"(acc[16 * n + 10]), "f"(acc[16 * n + 11]), "f"(acc[16 * n + 12]), "f"(acc[16 * n + 13]), "f"(acc[16 * n + 14]), "f"(acc[16 * n + 15]));
                }
            }
            fence_async_sm();
            warp_arrive(bars + B_STGU);
            bar_sync(3, 128);
            asm volatile("setmaxnreg.dec.sync.aligned.u32 152;");
            bar_arrive(7, 256);
        }
        if (wg == 1) {
            if (LAM_T0) __nanosleep(LAM_T0);
            const int cl = tid & 127, ch = (cl >> 6) * 512 + ((cl >> 3) & 1) * 256 + cb * 32 + ((cl >> 4) & 3) * 8 + (cl & 7);
            const float lr = bf2f(*(const unsigned short*)padd(p.lre, 2 * ch)), li = bf2f(*(const unsigned short*)padd(p.lim, 2 * ch));
            const float dt = __bfloat162float(__float2bfloat16(expf(bf2f(*(const unsigned short*)padd(p.ldt, 2 * ch)))));
            const float an = dt * li, th = an * 0.318309873342514f;
            float sn, cs, inv;
            sincospif(fmaf(rintf(0.5f * th), -2.f, th) + fmaf(an, 1.2841276653e-8f, fmaf(an, 0.318309873342514f, -th)), &sn, &cs);
            const float ex = expf(dt * lr), br = ex * cs, bi = ex * sn;
            asm("rcp.approx.f32 %0, %1;" : "=f"(inv) : "f"(lr * lr + li * li));
            inv += inv;
            const float cr = ((br - 1.f) * lr + bi * li) * inv, ci = (bi * lr - (br - 1.f) * li) * inv;
            sts128(sb + OFF_LAM + cl * 16, __float_as_uint(br), __float_as_uint(-bi), __float_as_uint(cr), __float_as_uint(-ci));
            mbar_wait(bars + B_EP, 0);
            bar_sync(8, 128);
            if (tid == 128) mbar_arrive(bars + B_LAM);
        }
        if (wg != 2) {
        if (wg == 0) bar_sync(4, 128); else bar_sync(7, 256);
        asm volatile("setmaxnreg.inc.sync.aligned.u32 160;");
        if (wg == 0) bar_sync(4, 128);
        float d[128];
        STAMPW(0, 10);
        Ring rg = ring_at(sb, role * 66 + wg * 16);
        cf lam[2];
        unsigned ep;
        gemm1(d, rg, ring_desc(sb, 0, 16, 1), ring_desc(sb, 16384, 16, 1), wg);
        const uint32_t lama = sb + OFF_LAM + wg * 1024 + w * 256 + (fresh_lane() & 28) * 4;
        mbar_wait_fast(bars + B_LAM, 0);
        lam[0] = lds_cf(lama); lam[1] = lds_cf(lama + 128);
        asm volatile("ld.shared.u32 %0, [%1];" : "=r"(ep) : "r"(bars + B_EPOCH) : "memory");
        asm volatile("setmaxnreg.inc.sync.aligned.u32 176;");
        cf L[2] = {lam[0], lam[1]};
#pragma unroll
        for (int i = 0; i < 4; i++) { L[0] = csq(L[0]); L[1] = csq(L[1]); }
        asm volatile("" : "+f"(L[0].x), "+f"(L[0].y), "+f"(L[1].x), "+f"(L[1].y)::"memory");
        wg_wait<0>();
        ring_release(rg, 8 * wg);
        pin(d);
        STAMPW(1, 11);
        {
            const int lane = fresh_lane(), g = lane >> 2, q = lane & 3, mi = lane >> 3, gl = lane & 7;
            cf f[2], fb2[2];
#pragma unroll
            for (int i = 0; i < 17; i++) {
#pragma unroll
                for (int h = 0; h < 2; h++) {
                    const int r = 4 * (i >> 1) + 2 * h + (i & 1), r2 = 32 + 4 * ((i - 1) >> 1) + 2 * h + ((i - 1) & 1);
                    if (i < 16) f[h] = i ? cfma(lam[h], f[h], {d[r], -d[64 + r]}) : cf{d[r], -d[64 + r]};
                    if (i > 0) fb2[h] = i > 1 ? cfma(lam[h], fb2[h], {d[r2], -d[64 + r2]}) : cf{d[r2], -d[64 + r2]};
                    if (i && (h || !(YS & 8))) YIELD_S1();
                }
            }
            const uint8_t* cbase = (const uint8_t*)g_carry + (tc * 16 + wg * 8 + cb) * 512 + w * 64;
            const uint8_t* cptr = padd(cbase, g * 8);
            const unsigned tag = ep & 15u;
#pragma unroll
            for (int h = 0; h < 2; h++) { f[h] = cfma(L[h], f[h], fb2[h]); L[h] = csq(L[h]); }
            cf s0[2], s1[2], s2[2];
#pragma unroll
            for (int h = 0; h < 2; h++) {
                s0[h] = {__shfl_sync(~0u, f[h].x, 0, 4), __shfl_sync(~0u, f[h].y, 0, 4)};
                s1[h] = {__shfl_sync(~0u, f[h].x, 1, 4), __shfl_sync(~0u, f[h].y, 1, 4)};
                s2[h] = {__shfl_sync(~0u, f[h].x, 2, 4), __shfl_sync(~0u, f[h].y, 2, 4)};
            }
#pragma unroll
            for (int h = 0; h < 2; h++) {
                s1[h] = cfma(L[h], s0[h], s1[h]);
                s2[h] = cfma(L[h], s1[h], s2[h]);
                f[h] = cfma(L[h], s2[h], f[h]);
                asm volatile("{.reg .pred p; .reg .b64 a; setp.eq.u32 p, %3, 3; mov.b64 a, {%1,%2}; @p st.relaxed.gpu.global.b64 [%0], a;}" ::"l"(cptr + h * 256),
                             "r"((__float_as_uint(f[h].x) & ~15u) | tag), "f"(f[h].y), "r"(q) : "memory");
            }
            STAMPX(2, 12);
            cf gam = lds_cf(lama + 8);
            cf st = csel(q & 2, csel(q & 1, s2[0], s1[0]), csel(q & 1, s0[0], {0.f, 0.f}));
            const cf st1 = csel(q & 2, csel(q & 1, s2[1], s1[1]), csel(q & 1, s0[1], {0.f, 0.f}));
            cptr = padd(cbase - 4 * 8192, (3 - mi) * 8192 + gl * 8);
            const int nprev = tc - 1 - mi;
            const uint8_t* hptr = padd(g_H + (size_t)(tc * 32 + wg * 16 + (cb & 6)) * 16384 + ((cb & 1) * 4 + w) * 1024, g * 64 + ((q ^ (g >> 1)) << 4));
            const uint32_t hm = 4 * (g & 1) + (q ^ (g >> 1)) == (cb & 1) * 4 + w ? ~1u : ~0u;
            float u[64];
            uint64_t fv[4] = {tag, tag, tag, tag};
            prescale<0>(u, d, gam);
            gather(fv, cptr, nprev);
#pragma unroll 1
            for (int h = 0;; h++) {
                const cf L2 = csq(L[0]), M = csq(L2);
                cf M4 = csq(csq(M));
                M4 = {__shfl_sync(~0u, M4.x, 4 * gl), __shfl_sync(~0u, M4.y, 4 * gl)};
                cf lq = cmul(gam, cmul(csel(q & 1, L[0], {1.f, 0.f}), csel(q & 2, L2, {1.f, 0.f})));
                st = cmul(gam, st);
                asm volatile("pmevent 1;" : "+f"(lq.x), "+f"(lq.y), "+f"(st.x), "+f"(st.y));
#pragma unroll 1
                for (unsigned n = 0; __any_sync(~0u, (((uint32_t)fv[0] ^ tag) | ((uint32_t)fv[1] ^ tag) | ((uint32_t)fv[2] ^ tag) | ((uint32_t)fv[3] ^ tag)) & 15u) && n < SPIN_LIMIT; n++) gather(fv, cptr, nprev);
                if (!h) STAMPX(53, 54);
                cf P = as_cf(fv[3]), pj[4];
#pragma unroll
                for (int a = 2; a >= 0; a--) P = cfma(M4, P, as_cf(fv[a]));
                cptr += 256;
                asm volatile("" : "+f"(P.x), "+f"(P.y)::"memory");
                gather(fv, cptr, h ? -1 : nprev);
#pragma unroll
                for (int j = 3; j >= 0; j--) pj[j] = {__shfl_sync(~0u, P.x, g + 8 * j), __shfl_sync(~0u, P.y, g + 8 * j)};
                st = cfma(lq, cfma(M, cfma(M, cfma(M, pj[3], pj[2]), pj[1]), pj[0]), st);
                if (!h) STAMPX(3, 13);
                uint32_t keep = sb >> 28;
                scan2(u, lam[0], st, hptr, hm, ep & ~hm, keep);
                warp_arrive(bars + B_HOWN + wg * 16 + h * 8 + keep);
                if (h) break;
                STAMPW(4, 14);
                lds128f(lama + 128, lam[0].x, lam[0].y, gam.x, gam.y);
                st = st1;
                L[0] = L[1];
                hptr += 8 * 16384;
                prescale<1>(u, d, gam);
            }
            STAMPW(5, 15);
        }
        if (wg == 0) bar_sync(4, 128); else bar_sync(8, 128);
        if (wg == 0) {
            asm volatile("setmaxnreg.dec.sync.aligned.u32 160;");
            float y[128];
            rg = ring_at(sb, role * 66 + 32);
            STAMP(6);
            STAMP(7);
            const uint64_t dA = ring_desc(sb, 0, 512, 2), dB = ring_desc(sb, 16384, 16, 1);
            gemm2(y, rg, dA, dB, 0);
            asm volatile("setmaxnreg.inc.sync.aligned.u32 184;");
            const int lane = fresh_lane(), g = lane >> 2, q = lane & 3;
            const int pg = 2 * (g & 3) + (g >> 2);
            float* op = (float*)padd(p.out + (size_t)(tc * 128 + 64 * (w & 1) + 8 * (w >> 1)) * 2048 + 1024 + cb * 128, pg * 8192 + q * 16);
            const uint32_t xa = sb + OFF_F + (16 * (w & 1) + 8 * (w >> 1) + pg) * 128 + (((q >> 1) ^ pg) << 4) + (q & 1) * 8;
#define HALF0(k) wg_fence(); peek(k < 63 ? rg.full + SL(k + 1) * 8 : bars + B_XD, PH(k + 1)); half_step<0, k>(y, dA, dB); wg_commit(); peek_wait(k < 63 ? rg.full + SL(k + 1) * 8 : bars + B_XD, PH(k + 1), rg.n);
            HALF0(60) HALF0(61) HALF0(62) HALF0(63)
            const uint64_t dB2 = ring_desc(sb >> 1, 16384, 16, 1);
            uint32_t xa0[8], xa1[8], dd[16];
#pragma unroll
            for (int i = 0; i < 8; i++) asm volatile("ld.shared.v2.b32 {%0,%1}, [%2];" : "=r"(dd[2 * i]), "=r"(dd[2 * i + 1]) : "r"(sb + OFF_LAM + q * 8 + 32 * i) : "memory");
            load_x4<0, 0>(xa0, xa);
            wg_fence();
            half_step<64, 64 - SKEW>(y, dA, dB2);
            wg_commit();
            wg_wait<1>();
#pragma unroll
            for (int i = 0; i < 64; i++) asm volatile("" : "+f"(y[i])::"memory");
            STAMP(16);
#define M1(n) if (4 + (n) < 4 * SKEW) mma_h<64, 65 - SKEW + (n) / 4, (n) % 4>(y, dA, dB2);
#define MM(n) if (4 + (n) / 2 * MPP < 4 * SKEW) { if (MPY) YIELD(); wg_fence(); M1((n) / 2 * MPP) M1((n) / 2 * MPP + 1) if (MPP > 2) { M1((n) / 2 * MPP + 2) } }
#define OUT4(R, U, X, n) out_piece<R, U>(y, dd, X[0], X[1], op); MM(n) out_piece<R, U + 1>(y, dd, X[2], X[3], op); MM(n + 2) \
                         out_piece<R, U + 2>(y, dd, X[4], X[5], op); MM(n + 4) out_piece<R, U + 3>(y, dd, X[6], X[7], op); MM(n + 6)
            load_x4<0, 4>(xa1, xa);
            OUT4(0, 0, xa0, 0)
            load_x4<1, 0>(xa0, xa);
            OUT4(0, 4, xa1, 8)
            wg_commit();
            load_x4<1, 4>(xa1, xa);
            OUT4(1, 0, xa0, 16)
            load_x4<2, 0>(xa0, xa);
            OUT4(1, 4, xa1, 16)
            STAMP(18);
            wg_wait<0>();
#pragma unroll
            for (int i = 64; i < 128; i++) asm volatile("" : "+f"(y[i])::"memory");
            STAMP(8);
            load_x4<2, 4>(xa1, xa);
            mbar_wait_fast(bars + B_XD + 8, 0);
            OUT4(2, 0, xa0, 16)
            load_x4<3, 0>(xa0, xa);
            OUT4(2, 4, xa1, 16)
            load_x4<3, 4>(xa1, xa);
            OUT4(3, 0, xa0, 16)
            OUT4(3, 4, xa1, 16)
            STAMP(9);
            return;
        }
        asm volatile("setmaxnreg.dec.sync.aligned.u32 152;");
        } else {
        if (nu) {
            constexpr int Y = YP2;
            cf T[8];
            ldtab_cf<2048>(T, TAB_T + t7 * 16);
            const uint32_t ep = get_epoch(bars);
            const int ka = pos_of(t7 >> 2);
            asm volatile("setp.eq.u32 p0, %0, 0;" ::"r"(__shfl_sync(~0u, t7, lane)));
            mbar_wait(bars + B_WSP, 0);
            mbar_wait(bars + B_FG, 0);
            uint32_t wd[4], wm[4], vo[32];
            const uint8_t* vp;
            int slot;
            const int kap0 = unit_of(role, 0, slot), al = 2 * kap0;
            const int kap1 = __shfl_sync(~0u, unit_of(role, 1, slot), 0);
            slot = __shfl_sync(~0u, slot, 0);
            cf be1 = twid(kap0 + 512 * q, 2048), be2 = csq(be1), be3 = cmul(be1, be2);
#pragma unroll
            for (int j = 0; j < 4; j++) {
                wd[j] = sb + OFF_WD + ((j + q) & 3) * WPITCH + (al & 15) + 2 * ka + 64 * q;
                wm[j] = sb + OFF_WM + (((role ? 3 : 4) - j - q) & 3) * WPITCH + (-al & 15) + 1024 - 2 * ka - 64 * q;
                wd[j] = __shfl_sync(~0u, wd[j], lane);
            }
#pragma unroll 1
            for (int u = 0; u < nu; u++) {
                const uint32_t buf = sb + OFF_P + u * 16384;
                float acc[64], za[32], zb[32], ya[32], yb[32], vv[64];
                const uint64_t dF = opaque(mkdesc(sb + OFF_F, 16, 1024, 1)), dB = opaque(mkdesc(buf, 4096, 512, 2));
                mbar_wait(bars + B_IN + u * 8, 0);
                if (!role) {
                    const uint32_t z = buf + w * 1024 + (fresh_lane() >> 2) * 128 + 64 + (fresh_lane() & 3) * 16;
#pragma unroll
                    for (int i = 0; i < 4; i++) sts128(z + i * 4096, 0, 0, 0, 0);
                    fence_async_sm();
                    bar_sync(3, 128);
                }
                STAMP3(22);
                wg_fence();
#pragma unroll
                for (int j = 0; j < 4; j++) mma128_ss<0, 0, 1>(acc, dF + j * 2, dB + j * 64, j);
                wg_commit();
                const bool pv = u && (role || !(fresh_lane() & 4));
                if (u) {
                    warp_arrive(bars + B_STG);
#pragma unroll
                    for (int k = 0; k < VS0; k++) {
                        if (k == VPOS0) hint_v(g_cnt + 64, role);
                        store_v(vo, vp, k, pv);
                    }
                    if (!role) { const uint32_t t = wm[0]; wm[0] = wm[1]; wm[1] = wm[2]; wm[2] = wm[3]; wm[3] = t; }
                }
                STAMP3(39);
                wg_wait<0>();
                pin(acc);
                STAMP3(30);
                uint32_t af[16], ag[16];
#pragma unroll
                for (int k = 0; k < 8; k++) {
                    uint32_t(&o)[16] = k < 4 ? af : ag;
                    const int c = k & 3;
#pragma unroll
                    for (int b = 0; b < 2; b++) {
                        const int i = 4 * (4 * ((k >> 2) * 2 + b) + c);
                        c2 x = mul2(c2{{acc[i], acc[i + 2]}, {acc[i + 1], acc[i + 3]}}, c2{T[2 * c], T[2 * c + 1]});
                        fin<Y>(x);
                        o[4 * c + b] = pk(x.a.x, x.a.y);
                        o[4 * c + 2 + b] = pk(x.b.x, x.b.y);
                    }
                    asm volatile("" : "+r"(o[4 * c]), "+r"(o[4 * c + 1]), "+r"(o[4 * c + 2]), "+r"(o[4 * c + 3])::"memory");
                    wg_fence();
                    mma64_rs<0>(k < 4 ? za : zb, o[4 * c], o[4 * c + 1], o[4 * c + 2], o[4 * c + 3], dF + c * 2, c);
                    if (k < 16 - VS0) store_v(vo, vp, VS0 + k, pv);
                    if (YT) YIELD();
                }
                wg_commit();
                STAMP3(31);
                mbar_wait(bars + B_WD, u & 1);
                uint32_t wr[16];
#pragma unroll
                for (int i = 0; i < 16; i++) wr[i] = lds16(wd[i >> 2] + 256 * ((i >> 1) & 1) + (i & 1) * 4 * WPITCH);
                wg_wait<0>();
                pin(za);
                pin(zb);
                pinu(af);
                pinu(ag);
                STAMP3(32);
#pragma unroll
                for (int jb = 0; jb < 4; jb++) {
                    const int i = 8 * jb;
                    c2 s0 = {{za[i], za[i + 4]}, {za[i + 1], za[i + 5]}}, s2 = {{za[i + 2], za[i + 6]}, {za[i + 3], za[i + 7]}};
                    c2 s1 = {{zb[i], zb[i + 4]}, {zb[i + 1], zb[i + 5]}}, s3 = {{zb[i + 2], zb[i + 6]}, {zb[i + 3], zb[i + 7]}};
                    s2 = mul2(s2, be1);
                    fin<Y>(s2);
                    bfly_tw<Y>(s0, s1, be2, s2, s3, be3);
                    bfly<Y>(s0, s2); bfly_mi<Y>(s1, s3);
                    c2 W[4];
#pragma unroll
                    for (int j = 0; j < 4; j++) {
                        W[j] = {{__uint_as_float(wr[4 * j] << 16), __uint_as_float(wr[4 * j + 1] << 16)}, {__uint_as_float(wr[4 * j + 2] << 16), __uint_as_float(wr[4 * j + 3] << 16)}};
                        if ((jb & 1) == 0)
                            asm volatile("@p0 ld.shared.v2.f32 {%0,%1}, [%2];" : "+f"(W[j].a.x), "+f"(W[j].a.y) : "r"(sb + OFF_WSP + u * 64 + jb * 16 + j * 8));
                    }
                    if (jb < 3) {
#pragma unroll
                        for (int k = 0; k < 16; k++) {
                            const int e = (k >> 1) & 1, pl = (k & 1) * 4 * WPITCH;
                            wr[k] = jb == 0 ? lds16(wd[k >> 2] + 512 + 256 * e + pl) : lds16(wm[k >> 2] - 512 * (jb - 1) - 256 * e + pl);
                        }
                    }
                    if (jb >= 2) {
#pragma unroll
                        for (int j = 0; j < 4; j++) { W[j].a.y = -W[j].a.y; W[j].b.y = -W[j].b.y; }
                    }
                    s0 = mul2(s0, W[0]); fin<Y>(s0);
                    s1 = mul2(s1, W[1]); fin<Y>(s1);
                    bfly_tw<Y>(s0, s2, W[2], s1, s3, W[3]);
                    bfly<Y>(s0, s1); bfly_mi<Y>(s2, s3);
                    af[4 * jb] = pk(s0.a.x, s0.b.x); af[4 * jb + 1] = pk(s3.a.x, s3.b.x); af[4 * jb + 2] = pk(s0.a.y, s0.b.y); af[4 * jb + 3] = pk(s3.a.y, s3.b.y);
                    ag[4 * jb] = pk(s1.a.x, s1.b.x); ag[4 * jb + 1] = pk(s2.a.x, s2.b.x); ag[4 * jb + 2] = pk(s1.a.y, s1.b.y); ag[4 * jb + 3] = pk(s2.a.y, s2.b.y);
                }
                pinu(af);
                pinu(ag);
                warp_arrive(bars + B_WFREE);
                wg_fence();
#pragma unroll
                for (int j = 0; j < 4; j++) mma64_rs<1>(ya, af[4 * j], af[4 * j + 1], af[4 * j + 2], af[4 * j + 3], dF + j * 128, j);
                wg_commit();
#pragma unroll
                for (int j = 0; j < 4; j++) mma64_rs<1>(yb, ag[4 * j], ag[4 * j + 1], ag[4 * j + 2], ag[4 * j + 3], dF + j * 128, j);
                wg_commit();
                STAMP3(33);
                {
                    const uint32_t a0 = buf + (mi & 1) * 4096 + (16 * w + 8 * (mi >> 1) + gl) * 64 + ((gl >> 1) << 4);
#pragma unroll
                    for (int h = 0; h < 2; h++) {
                        if (h == 0) { wg_wait<1>(); pin(ya); pinu(af); STAMP3(34); } else { wg_wait<0>(); pin(yb); pinu(ag); }
                        const float(&yy)[32] = h ? yb : ya;
#pragma unroll
                        for (int c = 0; c < 4; c++) {
                            const int i = 8 * ((c + 2 * h) & 3), k = 8 * ((c + 2 * h + 1) & 3) + 2;
                            c2 x = {cmulc({yy[i], yy[i + 1]}, T[2 * c]), cmulc({yy[k], yy[k + 1]}, T[2 * c])};
                            fin<Y>(x);
                            c2 y = {cmulc({yy[i + 4], yy[i + 5]}, T[2 * c + 1]), cmulc({yy[k + 4], yy[k + 5]}, T[2 * c + 1])};
                            fin<Y>(y);
                            stsm4((a0 ^ (c << 4)) + h * 8192, pk(x.a.x, y.a.x), pk(x.b.x, y.b.x), pk(x.a.y, y.a.y), pk(x.b.y, y.b.y));
                        }
                    }
                }
                STAMP3(38);
                fence_async_sm();
                bar_sync(3, 128);
                wg_fence();
#pragma unroll
                for (int j = 0; j < 4; j++) mma128_ss<0, 1, 1>(vv, dF + j * 128, dB + j * 64, j);
                wg_commit();
                STAMP3(35);
                const int lane = fresh_lane(), g = lane >> 2, q = lane & 3;
                vp = padd(g_X + (4 << 20) + w * (8 * 32768) + (role ? u : 1) * 16384 + slot * 64,
                                         (g >> 1) * 32768 + (role ? g & 1 : u) * 32 + (((q ^ (slot >> 1)) & 1) << 4) + (q >> 1) * 8);
                const uint32_t tmask = (((g & 1) == ((slot >> 3) & 1) || !role) && q == ((slot >> 1) & 2)) ? ~1u : ~0u, tbit = ep & ~tmask;
                be1 = twid(kap1 + 512 * q, 2048); be2 = csq(be1); be3 = cmul(be1, be2);
                asm volatile("pmevent 1;" : "+f"(be1.x), "+f"(be1.y), "+f"(be2.x), "+f"(be2.y), "+f"(be3.x), "+f"(be3.y), "+l"(vp)::"memory");
                wg_wait<0>();
                pin(vv);
                STAMP3(36);
#pragma unroll
                for (int k = 0; k < 16; k++) {
                    const int i = 8 * (k >> 1) + 2 * (k & 1);
                    vo[2 * k] = (pk(vv[i], vv[i + 1]) & tmask) | tbit;
                    vo[2 * k + 1] = pk(vv[i + 4], vv[i + 5]);
                }
                pinu(vo);
            }
            warp_arrive(bars + B_STG);
            const bool odd = fresh_lane() & 4;
#pragma unroll
            for (int k = 0; k < 16; k++) {
                if (k == VPOS) hint_v(g_cnt + 32 + nu * 32, 1);
                store_v(vo, vp, k, role || odd == (k >= 4));
            }
        }
        if (spare) return;
        }
        {
            constexpr int Y = YP3;
            uint32_t sp[8];
            cf tw[8];
            ldtab<2, 2048>(sp, TAB_SP + fb * 4096 + t7 * 16);
            ldtab_cf<16>(tw, TAB_TW3 + fb * 2048 + (t7 >> 2) * 64);
            const uint64_t dF = opaque(mkdesc(sb + OFF_F, 16, 1024, 1)), dB = opaque(mkdesc(sb + OFF_P + hf * 8192, 1024, 256, 3));
            const uint8_t* op = padd(p.out + (1024 + fb) * 2048 + fcb * 32 + hf * 16, (t7 >> 2) * 32768 + (q >> 1) * 16 + (q & 1) * 32);
            float acc[64], out[64];
            mbar_wait(bars + B_IN + 24, 0);
            mbar_wait(bars + B_FG, 1);
            STAMP(25);
            pinu(sp);
            wg_fence();
#pragma unroll
            for (int j = 0; j < 4; j++) {
                const uint64_t db = dB + (j >> 1) * 1024 + (j & 1) * 32;
                mma112_ss(acc, dF + j * 2, db + 64, j);
                if (j & 1) mma16_rs(acc, 0u, sp[2 * j], 0u, sp[2 * j + 1], db, 1);
                else mma16_rs(acc, sp[2 * j], 0u, sp[2 * j + 1], 0u, db, j);
            }
            wg_commit();
            wg_wait<0>();
            pin(acc);
            pinu(sp);
            warp_arrive(bars + B_P3M);
#pragma unroll
            for (int cl = 0; cl < 2; cl++) {
                c2 z[8];
#pragma unroll
                for (int n = 0; n < 8; n++) {
                    const int i = 4 * (2 * n + cl);
                    z[n] = {{acc[i], acc[i + 2]}, {acc[i + 1], acc[i + 3]}};
                }
                z[0] = {{z[0].a.x + z[0].a.y, z[0].a.x - z[0].a.y}, {z[0].b.x + z[0].b.y, z[0].b.x - z[0].b.y}};
                z[4] = mul2(z[4], tw[4]);
                fin<Y>(z[0], z[4]);
#pragma unroll
                for (int n = 1; n < 4; n++) {
                    const cf iw = n == 1 ? cf{0.38268343236508977f, 0.92387953251128674f}
                                         : (n == 2 ? cf{0.70710678118654752f, 0.70710678118654752f} : cf{0.92387953251128674f, 0.38268343236508977f});
                    c2 y = mul2(z[n], tw[n]);
                    fin<Y>(y);
                    const cf t = {tw[8 - n].x, -tw[8 - n].y};
                    c2 E = fma2(c2{{z[8 - n].a.x, -z[8 - n].a.y}, {z[8 - n].b.x, -z[8 - n].b.y}}, t, y);
                    fin<Y>(E);
                    z[n] = fma2(twm2(y, E), iw, E);
                    fin<Y>(z[n]);
                    z[8 - n] = {{fmaf(2.f, E.a.x, -z[n].a.x), fmaf(-2.f, E.a.y, z[n].a.y)}, {fmaf(2.f, E.b.x, -z[n].b.x), fmaf(-2.f, E.b.y, z[n].b.y)}};
                }
                dft8<false, Y>(z, tw);
#pragma unroll
                for (int m = 0; m < 8; m++) {
                    out[8 * m + 2 * cl] = z[m].a.x; out[8 * m + 2 * cl + 1] = z[m].b.x;
                    out[8 * m + 4 + 2 * cl] = z[m].a.y; out[8 * m + 5 + 2 * cl] = z[m].b.y;
                }
            }
            STAMP(26);
#pragma unroll
            for (int m = 0; m < 16; m++) {
                asm volatile("st.global.v4.f32 [%0], {%1,%2,%3,%4};" ::"l"(op + (m - 8) * (1 << 20)), "f"(out[4 * m]), "f"(out[4 * m + 1]), "f"(out[4 * m + 2]), "f"(out[4 * m + 3]) : "memory");
                if (PACE_O && m < 15 && m % PACE_ON == PACE_ON - 1)
                    asm volatile("{.reg .pred p; mbarrier.test_wait.parity.shared::cta.b64 p, [%0], 0; @!p nanosleep.u32 %1;}" ::"r"(bars + B_DONE), "n"(PACE_O) : "memory");
            }
            STAMP(27);
        }
    }
}

typedef CUresult (*EncodeFn)(CUtensorMap*, CUtensorMapDataType, cuuint32_t, void*, const cuuint64_t*, const cuuint64_t*, const cuuint32_t*,
                             const cuuint32_t*, CUtensorMapInterleave, CUtensorMapSwizzle, CUtensorMapL2promotion, CUtensorMapFloatOOBfill);

static CUtensorMap make_map(EncodeFn enc, const void* ptr, int rank, const cuuint64_t* dims, const cuuint64_t* strides, const cuuint32_t* box,
                            CUtensorMapSwizzle swz, CUtensorMapL2promotion promo, CUtensorMapDataType dt = CU_TENSOR_MAP_DATA_TYPE_BFLOAT16) {
    CUtensorMap m;
    const cuuint32_t es[5] = {1, 1, 1, 1, 1};
    enc(&m, dt, rank, const_cast<void*>(ptr), dims, strides, box, es, CU_TENSOR_MAP_INTERLEAVE_NONE, swz, promo,
        CU_TENSOR_MAP_FLOAT_OOB_FILL_NONE);
    return m;
}

extern "C" void kernel_launch(void* const* d_in, const int* in_sizes, int n_in, void* d_out, int out_size) {
    void* fn = nullptr;
    cudaDriverEntryPointQueryResult qr;
    cudaGetDriverEntryPoint("cuTensorMapEncodeTiled", &fn, cudaEnableDefault, &qr);
    EncodeFn enc = (EncodeFn)fn;
    void* pX;
    cudaGetSymbolAddress(&pX, g_X);
    const CUtensorMapL2promotion P256 = CU_TENSOR_MAP_L2_PROMOTION_L2_256B, P0 = CU_TENSOR_MAP_L2_PROMOTION_NONE;

    const cuuint64_t dX[5] = {1024, 2, 4, 16, 16}, sX[4] = {2048, 32 * 2048, 2 * 2048, 128 * 2048};
    const cuuint32_t bX[5] = {64, 2, 4, 16, 1};
    CUtensorMap tmX = make_map(enc, d_in[3], 5, dX, sX, bX, CU_TENSOR_MAP_SWIZZLE_128B, P256);
    const cuuint64_t dXd[4] = {64, 2048, 2, 16}, sXd[3] = {2048, 64 * 2048, 128};
    const cuuint32_t bXd[4] = {64, 16, 2, 2};
    CUtensorMap tmXd = make_map(enc, d_in[3], 4, dXd, sXd, bXd, CU_TENSOR_MAP_SWIZZLE_128B, P256);
    const cuuint64_t dB[4] = {1024, 8, 4, 32}, sB[3] = {2048, 256 * 2048, 8 * 2048};
    const cuuint32_t bB4[4] = {64, 8, 2, 4};
    CUtensorMap tmBre = make_map(enc, d_in[6], 4, dB, sB, bB4, CU_TENSOR_MAP_SWIZZLE_128B, P256);
    CUtensorMap tmBim = make_map(enc, d_in[7], 4, dB, sB, bB4, CU_TENSOR_MAP_SWIZZLE_128B, P256);
    const cuuint64_t dC[5] = {1024, 2, 4, 2, 64}, sC[4] = {2048, 4 * 2048, 2 * 2048, 16 * 2048};
    const cuuint32_t bC[5] = {64, 2, 4, 2, 4};
    CUtensorMap tmCre = make_map(enc, d_in[8], 5, dC, sC, bC, CU_TENSOR_MAP_SWIZZLE_128B, P256);
    CUtensorMap tmCim = make_map(enc, d_in[9], 5, dC, sC, bC, CU_TENSOR_MAP_SWIZZLE_128B, P256);

    const cuuint64_t dU[2] = {8192, 256}, sU[1] = {16384};
    const cuuint32_t bU[2] = {64, 64};
    CUtensorMap tmUst = make_map(enc, pX, 2, dU, sU, bU, CU_TENSOR_MAP_SWIZZLE_128B, P0);
    const cuuint64_t dF[2] = {512 * 1026 / 8, 4}, sF[1] = {512 * 1026};
    const cuuint32_t bF[2] = {WPITCH / 8, 4};
    CUtensorMap tmWr = make_map(enc, d_in[1], 2, dF, sF, bF, CU_TENSOR_MAP_SWIZZLE_NONE, P0, CU_TENSOR_MAP_DATA_TYPE_UINT64);
    CUtensorMap tmWi = make_map(enc, d_in[2], 2, dF, sF, bF, CU_TENSOR_MAP_SWIZZLE_NONE, P0, CU_TENSOR_MAP_DATA_TYPE_UINT64);

    const cuuint64_t dA[3] = {1024, 64, 32}, sA[2] = {32 * 2048, 2048};
    const cuuint32_t bA[3] = {32, 64, 1};
    CUtensorMap tmXa = make_map(enc, d_in[0], 3, dA, sA, bA, CU_TENSOR_MAP_SWIZZLE_64B, XA_PROMO);

    Params p;
    p.wr = (const __nv_bfloat16*)d_in[1];
    p.wi = (const __nv_bfloat16*)d_in[2];
    p.lre = (const __nv_bfloat16*)d_in[4];
    p.lim = (const __nv_bfloat16*)d_in[5];
    p.ldt = (const __nv_bfloat16*)d_in[10];
    p.dsk = (const __nv_bfloat16*)d_in[11];
    p.out = (float*)d_out;
    int dev = 0, sms = 0;
    cudaGetDevice(&dev);
    cudaDeviceGetAttribute(&sms, cudaDevAttrMultiProcessorCount, dev);
    auto kernel = sms == 132 ? fused_kernel<true> : fused_kernel<false>;
    cudaFuncSetAttribute(kernel, cudaFuncAttributeMaxDynamicSharedMemorySize, SMEM_BYTES);
    kernel<<<132, 512, SMEM_BYTES>>>(tmX, tmBre, tmBim, tmCre, tmCim, tmXd, tmUst, tmWr, tmWi, tmXa, p);
}
```

```cpp
#include <cuda_runtime.h>
#include <cuda.h>
#include <cuda_bf16.h>
#include <stdint.h>

#define NST 5
#define WPITCH 1056
#define OFF_P (NST * 32768)
#define OFF_F (OFF_P + 32768)
#define OFF_WD (OFF_F + 8192)
#define OFF_WM (OFF_WD + 8 * WPITCH)
#define OFF_BAR (OFF_F + 32768)
#define OFF_LAM (OFF_BAR + 432)
#define OFF_WSP (OFF_LAM + 2048)
#define OFF_PROF (OFF_WSP + 128)
#define SMEM_BYTES OFF_PROF
#define B_FULL 0
#define B_HL 40
#define B_EP 120
#define B_HR 128
#define B_XD 144
#define B_FG 160
#define B_WSP 168
#define B_WD 176
#define B_DONE 184
#define B_LD 192
#define B_RAW 200
#define B_LAM 208
#define B_IN 216
#define B_XIN 248
#define B_EMPTY 256
#define B_STG 320
#define B_WFREE 328
#define B_HOWN 336
#define B_STGU 368
#define B_P3M 384
#define B_EPOCH 416

#define PACE_U 20
#define PACE_V 20
#define XA_PACE 200
#define XA_PACE2 100
#define XA_TAB 0
#define XA_TABP 200
#define PACE_O 200
#define PACE_ON 2
#define XA_PROMO CU_TENSOR_MAP_L2_PROMOTION_L2_128B
#define TAB_T0 500
#define LAM_T0 1000
#define DEFER 0
#define UHINT 1
#define VPOS 2
#define VPOS0 8
#define GOV_T 100
#define GOV_K0 16
#define GOV_N 22
#define TIDMAP threadIdx.x
#define U1POS 2
#define WPFB B_XIN
#define VS0 16
#define YT 1
#define MPP 2
#define MPY 0
#define STAG 1
#define P1H 1
#define XA_N0 2
#define XA_T0 0
#define PACE_X 200
#define SKEW 4
#define SPIN_LIMIT (1u << 15)

__device__ __align__(1024) uint8_t g_X[8 << 20];
__device__ __align__(1024) uint8_t g_H[8 << 20];
__device__ __align__(1024) uint4 g_carry[16 * 512];
__device__ __align__(128) unsigned g_cnt[128];
__device__ __align__(128) unsigned g_epoch[132 * 8];

#define STAMP(i) do { } while (0)
#define STAMPO(i, o) do { } while (0)
#define STAMPW(a, b) do { } while (0)
#define STAMPX(a, b) do { } while (0)
#define STAMP5(i) do { } while (0)
#define STAMP6(i) do { } while (0)
#define STAMP3(i) do { } while (0)

#define TAB_FG 0
#define TAB_G 8192
#define TAB_F1 40960
#define TAB_T 49152
#define TAB_SP 57344
#define TAB_TW1 73728
#define TAB_TW3 75776
#define TAB_PC 83968
__device__ __align__(1024) const uint32_t g_tab[21248] = {
0x80003d80,0x80003d80,0x80003d80,0x80003d80,0x80003d80,0x80003d80,0x80003d80,0x80003d80,0x80003d80,0x80003d80,0x80003d80,0x80003d80,0x80003d80,0x80003d80,0x80003d80,0x80003d80,
0x80003d80,0x80003d80,0x80003d80,0x80003d80,0x80003d80,0x80003d80,0x80003d80,0x80003d80,0x80003d80,0x80003d80,0x80003d80,0x80003d80,0x80003d80,0x80003d80,0x80003d80,0x80003d80,
0x3d353d35,0x3d35bd35,0xbd35bd35,0xbd353d35,0x80003d80,0x3d800000,0x8000bd80,0xbd800000,0x3d353d35,0x3d35bd35,0xbd35bd35,0xbd353d35,0x80003d80,0x3d800000,0x8000bd80,0xbd800000,
0x3d353d35,0x3d35bd35,0xbd35bd35,0xbd353d35,0x80003d80,0x3d800000,0x8000bd80,0xbd800000,0x3d353d35,0x3d35bd35,0xbd35bd35,0xbd353d35,0x80003d80,0x3d800000,0x8000bd80,0xbd800000,
0x3d800000,0x3d6dbcc4,0x3d35bd35,0x3cc4bd6d,0x3d7bbc48,0x3d55bd0e,0x3d0ebd55,0x3c48bd7b,0x80003d80,0x3cc43d6d,0x3d353d35,0x3d6d3cc4,0x3c483d7b,0x3d0e3d55,0x3d553d0e,0x3d7b3c48,
0xbd800000,0xbd6d3cc4,0xbd353d35,0xbcc43d6d,0xbd7b3c48,0xbd553d0e,0xbd0e3d55,0xbc483d7b,0x8000bd80,0xbcc4bd6d,0xbd35bd35,0xbd6dbcc4,0xbc48bd7b,0xbd0ebd55,0xbd55bd0e,0xbd7bbc48,
0x3d0ebd55,0xbd7bbc48,0x3c483d7b,0x3d55bd0e,0x3d800000,0xbcc4bd6d,0xbd353d35,0x3d6d3cc4,0x3d553d0e,0x3c48bd7b,0xbd7b3c48,0x3d0e3d55,0x80003d80,0x3d6dbcc4,0xbd35bd35,0xbcc43d6d,
0xbd0e3d55,0x3d7b3c48,0xbc48bd7b,0xbd553d0e,0xbd800000,0x3cc43d6d,0x3d35bd35,0xbd6dbcc4,0xbd55bd0e,0xbc483d7b,0x3d7bbc48,0xbd0ebd55,0x8000bd80,0xbd6d3cc4,0x3d353d35,0x3cc4bd6d,
0x80003d80,0x3d353d35,0x3d800000,0x3d35bd35,0x3cc43d6d,0x3d6d3cc4,0x3d6dbcc4,0x3cc4bd6d,0x8000bd80,0xbd35bd35,0xbd800000,0xbd353d35,0xbcc4bd6d,0xbd6dbcc4,0xbd6d3cc4,0xbcc43d6d,
0x80003d80,0x3d353d35,0x3d800000,0x3d35bd35,0x3cc43d6d,0x3d6d3cc4,0x3d6dbcc4,0x3cc4bd6d,0x8000bd80,0xbd35bd35,0xbd800000,0xbd353d35,0xbcc4bd6d,0xbd6dbcc4,0xbd6d3cc4,0xbcc43d6d,
0x3d6d3cc4,0xbcc4bd6d,0xbcc43d6d,0x3d6dbcc4,0x80003d80,0x3d35bd35,0xbd800000,0x3d353d35,0xbd6dbcc4,0x3cc43d6d,0x3cc4bd6d,0xbd6d3cc4,0x8000bd80,0xbd353d35,0x3d800000,0xbd35bd35,
0x3d6d3cc4,0xbcc4bd6d,0xbcc43d6d,0x3d6dbcc4,0x80003d80,0x3d35bd35,0xbd800000,0x3d353d35,0xbd6dbcc4,0x3cc43d6d,0x3cc4bd6d,0xbd6d3cc4,0x8000bd80,0xbd353d35,0x3d800000,0xbd35bd35,
0x3d800000,0x3cc4bd6d,0xbd35bd35,0xbd6d3cc4,0x3d55bd0e,0xbc48bd7b,0xbd7bbc48,0xbd0e3d55,0x8000bd80,0xbd6dbcc4,0xbd353d35,0x3cc43d6d,0xbd0ebd55,0xbd7b3c48,0xbc483d7b,0x3d553d0e,
0xbd800000,0xbcc43d6d,0x3d353d35,0x3d6dbcc4,0xbd553d0e,0x3c483d7b,0x3d7b3c48,0x3d0ebd55,0x80003d80,0x3d6d3cc4,0x3d35bd35,0xbcc4bd6d,0x3d0e3d55,0x3d7bbc48,0x3c48bd7b,0xbd55bd0e,
0x3c48bd7b,0xbd0e3d55,0x3d55bd0e,0xbd7b3c48,0x3d800000,0xbd6dbcc4,0x3d353d35,0xbcc4bd6d,0xbd7bbc48,0x3d553d0e,0xbd0ebd55,0x3c483d7b,0x8000bd80,0xbcc43d6d,0x3d35bd35,0xbd6d3cc4,
0xbc483d7b,0x3d0ebd55,0xbd553d0e,0x3d7bbc48,0xbd800000,0x3d6d3cc4,0xbd35bd35,0x3cc43d6d,0x3d7b3c48,0xbd55bd0e,0x3d0e3d55,0xbc48bd7b,0x80003d80,0x3cc4bd6d,0xbd353d35,0x3d6dbcc4,
0x3d800000,0x3d800000,0x3d800000,0x3d800000,0x3d800000,0x3d800000,0x3d800000,0x3d800000,0x3d800000,0x3d800000,0x3d800000,0x3d800000,0x3d800000,0x3d800000,0x3d800000,0x3d800000,
0x3d800000,0x3d800000,0x3d800000,0x3d800000,0x3d800000,0x3d800000,0x3d800000,0x3d800000,0x3d800000,0x3d800000,0x3d800000,0x3d800000,0x3d800000,0x3d800000,0x3d800000,0x3d800000,
0x3d35bd35,0xbd35bd35,0xbd353d35,0x3d353d35,0x3d800000,0xbd80,0xbd800000,0x3d80,0x3d35bd35,0xbd35bd35,0xbd353d35,0x3d353d35,0x3d800000,0xbd80,0xbd800000,0x3d80,
0x3d35bd35,0xbd35bd35,0xbd353d35,0x3d353d35,0x3d800000,0xbd80,0xbd800000,0x3d80,0x3d35bd35,0xbd35bd35,0xbd353d35,0x3d353d35,0x3d800000,0xbd80,0xbd800000,0x3d80,
0xbd80,0xbcc4bd6d,0xbd35bd35,0xbd6dbcc4,0xbc48bd7b,0xbd0ebd55,0xbd55bd0e,0xbd7bbc48,0x3d800000,0x3d6dbcc4,0x3d35bd35,0x3cc4bd6d,0x3d7bbc48,0x3d55bd0e,0x3d0ebd55,0x3c48bd7b,
0x3d80,0x3cc43d6d,0x3d353d35,0x3d6d3cc4,0x3c483d7b,0x3d0e3d55,0x3d553d0e,0x3d7b3c48,0xbd800000,0xbd6d3cc4,0xbd353d35,0xbcc43d6d,0xbd7b3c48,0xbd553d0e,0xbd0e3d55,0xbc483d7b,
0xbd55bd0e,0xbc483d7b,0x3d7bbc48,0xbd0ebd55,0xbd80,0xbd6d3cc4,0x3d353d35,0x3cc4bd6d,0x3d0ebd55,0xbd7bbc48,0x3c483d7b,0x3d55bd0e,0x3d800000,0xbcc4bd6d,0xbd353d35,0x3d6d3cc4,
0x3d553d0e,0x3c48bd7b,0xbd7b3c48,0x3d0e3d55,0x3d80,0x3d6dbcc4,0xbd35bd35,0xbcc43d6d,0xbd0e3d55,0x3d7b3c48,0xbc48bd7b,0xbd553d0e,0xbd800000,0x3cc43d6d,0x3d35bd35,0xbd6dbcc4,
0x3d800000,0x3d35bd35,0xbd80,0xbd35bd35,0x3d6dbcc4,0x3cc4bd6d,0xbcc4bd6d,0xbd6dbcc4,0xbd800000,0xbd353d35,0x3d80,0x3d353d35,0xbd6d3cc4,0xbcc43d6d,0x3cc43d6d,0x3d6d3cc4,
0x3d800000,0x3d35bd35,0xbd80,0xbd35bd35,0x3d6dbcc4,0x3cc4bd6d,0xbcc4bd6d,0xbd6dbcc4,0xbd800000,0xbd353d35,0x3d80,0x3d353d35,0xbd6d3cc4,0xbcc43d6d,0x3cc43d6d,0x3d6d3cc4,
0x3cc4bd6d,0xbd6d3cc4,0x3d6d3cc4,0xbcc4bd6d,0x3d800000,0xbd35bd35,0x3d80,0x3d35bd35,0xbcc43d6d,0x3d6dbcc4,0xbd6dbcc4,0x3cc43d6d,0xbd800000,0x3d353d35,0xbd80,0xbd353d35,
0x3cc4bd6d,0xbd6d3cc4,0x3d6d3cc4,0xbcc4bd6d,0x3d800000,0xbd35bd35,0x3d80,0x3d35bd35,0xbcc43d6d,0x3d6dbcc4,0xbd6dbcc4,0x3cc43d6d,0xbd800000,0x3d353d35,0xbd80,0xbd353d35,
0xbd80,0xbd6dbcc4,0xbd353d35,0x3cc43d6d,0xbd0ebd55,0xbd7b3c48,0xbc483d7b,0x3d553d0e,0xbd800000,0xbcc43d6d,0x3d353d35,0x3d6dbcc4,0xbd553d0e,0x3c483d7b,0x3d7b3c48,0x3d0ebd55,
0x3d80,0x3d6d3cc4,0x3d35bd35,0xbcc4bd6d,0x3d0e3d55,0x3d7bbc48,0x3c48bd7b,0xbd55bd0e,0x3d800000,0x3cc4bd6d,0xbd35bd35,0xbd6d3cc4,0x3d55bd0e,0xbc48bd7b,0xbd7bbc48,0xbd0e3d55,
0xbd7bbc48,0x3d553d0e,0xbd0ebd55,0x3c483d7b,0xbd80,0xbcc43d6d,0x3d35bd35,0xbd6d3cc4,0xbc483d7b,0x3d0ebd55,0xbd553d0e,0x3d7bbc48,0xbd800000,0x3d6d3cc4,0xbd35bd35,0x3cc43d6d,
0x3d7b3c48,0xbd55bd0e,0x3d0e3d55,0xbc48bd7b,0x3d80,0x3cc4bd6d,0xbd353d35,0x3d6dbcc4,0x3c48bd7b,0xbd0e3d55,0x3d55bd0e,0xbd7b3c48,0x3d800000,0xbd6dbcc4,0x3d353d35,0xbcc4bd6d,
0x80003d80,0x8000bd80,0x80003d80,0x8000bd80,0x3d800000,0xbd800000,0x3d800000,0xbd800000,0x80003d80,0x8000bd80,0x80003d80,0x8000bd80,0x3d800000,0xbd800000,0x3d800000,0xbd800000,
0x80003d80,0x8000bd80,0x80003d80,0x8000bd80,0x3d800000,0xbd800000,0x3d800000,0xbd800000,0x80003d80,0x8000bd80,0x80003d80,0x8000bd80,0x3d800000,0xbd800000,0x3d800000,0xbd800000,
0x3d35bd35,0x3d353d35,0xbd353d35,0xbd35bd35,0x80003d80,0xbd800000,0x8000bd80,0x3d800000,0x3d35bd35,0x3d353d35,0xbd353d35,0xbd35bd35,0x80003d80,0xbd800000,0x8000bd80,0x3d800000,
0x3d35bd35,0x3d353d35,0xbd353d35,0xbd35bd35,0x80003d80,0xbd800000,0x8000bd80,0x3d800000,0x3d35bd35,0x3d353d35,0xbd353d35,0xbd35bd35,0x80003d80,0xbd800000,0x8000bd80,0x3d800000,
0x3d800000,0xbd6d3cc4,0x3d35bd35,0xbcc43d6d,0xbc48bd7b,0x3d0e3d55,0xbd55bd0e,0x3d7b3c48,0x80003d80,0xbcc4bd6d,0x3d353d35,0xbd6dbcc4,0x3d7bbc48,0xbd553d0e,0x3d0ebd55,0xbc483d7b,
0xbd800000,0x3d6dbcc4,0xbd353d35,0x3cc4bd6d,0x3c483d7b,0xbd0ebd55,0x3d553d0e,0xbd7bbc48,0x8000bd80,0x3cc43d6d,0xbd35bd35,0x3d6d3cc4,0xbd7b3c48,0x3d55bd0e,0xbd0e3d55,0x3c48bd7b,
0xbd55bd0e,0x3c48bd7b,0x3d7bbc48,0x3d0e3d55,0x3d800000,0x3cc43d6d,0xbd353d35,0xbd6dbcc4,0x3d0ebd55,0x3d7b3c48,0x3c483d7b,0xbd553d0e,0x80003d80,0xbd6d3cc4,0xbd35bd35,0x3cc4bd6d,
0x3d553d0e,0xbc483d7b,0xbd7b3c48,0xbd0ebd55,0xbd800000,0xbcc4bd6d,0x3d35bd35,0x3d6d3cc4,0xbd0e3d55,0xbd7bbc48,0xbc48bd7b,0x3d55bd0e,0x8000bd80,0x3d6dbcc4,0x3d353d35,0xbcc43d6d,
0x80003d80,0xbd35bd35,0x3d800000,0xbd353d35,0x3d6dbcc4,0xbcc43d6d,0xbcc4bd6d,0x3d6d3cc4,0x8000bd80,0x3d353d35,0xbd800000,0x3d35bd35,0xbd6d3cc4,0x3cc4bd6d,0x3cc43d6d,0xbd6dbcc4,
0x80003d80,0xbd35bd35,0x3d800000,0xbd353d35,0x3d6dbcc4,0xbcc43d6d,0xbcc4bd6d,0x3d6d3cc4,0x8000bd80,0x3d353d35,0xbd800000,0x3d35bd35,0xbd6d3cc4,0x3cc4bd6d,0x3cc43d6d,0xbd6dbcc4,
0x3cc4bd6d,0x3d6dbcc4,0x3d6d3cc4,0x3cc43d6d,0x80003d80,0xbd353d35,0xbd800000,0xbd35bd35,0xbcc43d6d,0xbd6d3cc4,0xbd6dbcc4,0xbcc4bd6d,0x8000bd80,0x3d35bd35,0x3d800000,0x3d353d35,
0x3cc4bd6d,0x3d6dbcc4,0x3d6d3cc4,0x3cc43d6d,0x80003d80,0xbd353d35,0xbd800000,0xbd35bd35,0xbcc43d6d,0xbd6d3cc4,0xbd6dbcc4,0xbcc4bd6d,0x8000bd80,0x3d35bd35,0x3d800000,0x3d353d35,
0x3d800000,0xbcc43d6d,0xbd35bd35,0x3d6dbcc4,0xbd0ebd55,0x3d7bbc48,0xbc483d7b,0xbd55bd0e,0x8000bd80,0x3d6d3cc4,0xbd353d35,0xbcc4bd6d,0xbd553d0e,0xbc48bd7b,0x3d7b3c48,0xbd0e3d55,
0xbd800000,0x3cc4bd6d,0x3d353d35,0xbd6d3cc4,0x3d0e3d55,0xbd7b3c48,0x3c48bd7b,0x3d553d0e,0x80003d80,0xbd6dbcc4,0x3d35bd35,0x3cc43d6d,0x3d55bd0e,0x3c483d7b,0xbd7bbc48,0x3d0ebd55,
0xbd7bbc48,0xbd55bd0e,0xbd0ebd55,0xbc48bd7b,0x3d800000,0x3d6d3cc4,0x3d353d35,0x3cc43d6d,0xbc483d7b,0xbd0e3d55,0xbd553d0e,0xbd7b3c48,0x8000bd80,0x3cc4bd6d,0x3d35bd35,0x3d6dbcc4,
0x3d7b3c48,0x3d553d0e,0x3d0e3d55,0x3c483d7b,0xbd800000,0xbd6dbcc4,0xbd35bd35,0xbcc4bd6d,0x3c48bd7b,0x3d0ebd55,0x3d55bd0e,0x3d7bbc48,0x80003d80,0xbcc43d6d,0xbd353d35,0xbd6d3cc4,
0x3d800000,0xbd800000,0x3d800000,0xbd800000,0xbd80,0x3d80,0xbd80,0x3d80,0x3d800000,0xbd800000,0x3d800000,0xbd800000,0xbd80,0x3d80,0xbd80,0x3d80,
0x3d800000,0xbd800000,0x3d800000,0xbd800000,0xbd80,0x3d80,0xbd80,0x3d80,0x3d800000,0xbd800000,0x3d800000,0xbd800000,0xbd80,0x3d80,0xbd80,0x3d80,
0xbd35bd35,0x3d35bd35,0x3d353d35,0xbd353d35,0x3d800000,0x3d80,0xbd800000,0xbd80,0xbd35bd35,0x3d35bd35,0x3d353d35,0xbd353d35,0x3d800000,0x3d80,0xbd800000,0xbd80,
0xbd35bd35,0x3d35bd35,0x3d353d35,0xbd353d35,0x3d800000,0x3d80,0xbd800000,0xbd80,0xbd35bd35,0x3d35bd35,0x3d353d35,0xbd353d35,0x3d800000,0x3d80,0xbd800000,0xbd80,
0xbd80,0x3cc43d6d,0xbd35bd35,0x3d6d3cc4,0xbd7b3c48,0x3d55bd0e,0xbd0e3d55,0x3c48bd7b,0x3d800000,0xbd6d3cc4,0x3d35bd35,0xbcc43d6d,0xbc48bd7b,0x3d0e3d55,0xbd55bd0e,0x3d7b3c48,
0x3d80,0xbcc4bd6d,0x3d353d35,0xbd6dbcc4,0x3d7bbc48,0xbd553d0e,0x3d0ebd55,0xbc483d7b,0xbd800000,0x3d6dbcc4,0xbd353d35,0x3cc4bd6d,0x3c483d7b,0xbd0ebd55,0x3d553d0e,0xbd7bbc48,
0xbd0e3d55,0xbd7bbc48,0xbc48bd7b,0x3d55bd0e,0xbd80,0x3d6dbcc4,0x3d353d35,0xbcc43d6d,0xbd55bd0e,0x3c48bd7b,0x3d7bbc48,0x3d0e3d55,0x3d800000,0x3cc43d6d,0xbd353d35,0xbd6dbcc4,
0x3d0ebd55,0x3d7b3c48,0x3c483d7b,0xbd553d0e,0x3d80,0xbd6d3cc4,0xbd35bd35,0x3cc4bd6d,0x3d553d0e,0xbc483d7b,0xbd7b3c48,0xbd0ebd55,0xbd800000,0xbcc4bd6d,0x3d35bd35,0x3d6d3cc4,
0x3d800000,0xbd353d35,0xbd80,0x3d353d35,0xbcc4bd6d,0x3d6d3cc4,0xbd6d3cc4,0x3cc4bd6d,0xbd800000,0x3d35bd35,0x3d80,0xbd35bd35,0x3cc43d6d,0xbd6dbcc4,0x3d6dbcc4,0xbcc43d6d,
0x3d800000,0xbd353d35,0xbd80,0x3d353d35,0xbcc4bd6d,0x3d6d3cc4,0xbd6d3cc4,0x3cc4bd6d,0xbd800000,0x3d35bd35,0x3d80,0xbd35bd35,0x3cc43d6d,0xbd6dbcc4,0x3d6dbcc4,0xbcc43d6d,
0xbd6dbcc4,0xbcc4bd6d,0x3cc4bd6d,0x3d6dbcc4,0x3d800000,0x3d353d35,0x3d80,0xbd353d35,0x3d6d3cc4,0x3cc43d6d,0xbcc43d6d,0xbd6d3cc4,0xbd800000,0xbd35bd35,0xbd80,0x3d35bd35,
0xbd6dbcc4,0xbcc4bd6d,0x3cc4bd6d,0x3d6dbcc4,0x3d800000,0x3d353d35,0x3d80,0xbd353d35,0x3d6d3cc4,0x3cc43d6d,0xbcc43d6d,0xbd6d3cc4,0xbd800000,0xbd35bd35,0xbd80,0x3d35bd35,
0xbd80,0x3d6d3cc4,0xbd353d35,0xbcc4bd6d,0xbd553d0e,0xbc48bd7b,0x3d7b3c48,0xbd0e3d55,0xbd800000,0x3cc4bd6d,0x3d353d35,0xbd6d3cc4,0x3d0e3d55,0xbd7b3c48,0x3c48bd7b,0x3d553d0e,
0x3d80,0xbd6dbcc4,0x3d35bd35,0x3cc43d6d,0x3d55bd0e,0x3c483d7b,0xbd7bbc48,0x3d0ebd55,0x3d800000,0xbcc43d6d,0xbd35bd35,0x3d6dbcc4,0xbd0ebd55,0x3d7bbc48,0xbc483d7b,0xbd55bd0e,
0xbc483d7b,0xbd0e3d55,0xbd553d0e,0xbd7b3c48,0xbd80,0x3cc4bd6d,0x3d35bd35,0x3d6dbcc4,0x3d7b3c48,0x3d553d0e,0x3d0e3d55,0x3c483d7b,0xbd800000,0xbd6dbcc4,0xbd35bd35,0xbcc4bd6d,
0x3c48bd7b,0x3d0ebd55,0x3d55bd0e,0x3d7bbc48,0x3d80,0xbcc43d6d,0xbd353d35,0xbd6d3cc4,0xbd7bbc48,0xbd55bd0e,0xbd0ebd55,0xbc48bd7b,0x3d800000,0x3d6d3cc4,0x3d353d35,0x3cc43d6d,
0x80003d80,0x80003d80,0x80003d80,0x80003d80,0x8000bd80,0x8000bd80,0x8000bd80,0x8000bd80,0x80003d80,0x80003d80,0x80003d80,0x80003d80,0x8000bd80,0x8000bd80,0x8000bd80,0x8000bd80,
0x80003d80,0x80003d80,0x80003d80,0x80003d80,0x8000bd80,0x8000bd80,0x8000bd80,0x8000bd80,0x80003d80,0x80003d80,0x80003d80,0x80003d80,0x8000bd80,0x8000bd80,0x8000bd80,0x8000bd80,
0xbd35bd35,0xbd353d35,0x3d353d35,0x3d35bd35,0x80003d80,0x3d800000,0x8000bd80,0xbd800000,0xbd35bd35,0xbd353d35,0x3d353d35,0x3d35bd35,0x80003d80,0x3d800000,0x8000bd80,0xbd800000,
0xbd35bd35,0xbd353d35,0x3d353d35,0x3d35bd35,0x80003d80,0x3d800000,0x8000bd80,0xbd800000,0xbd35bd35,0xbd353d35,0x3d353d35,0x3d35bd35,0x80003d80,0x3d800000,0x8000bd80,0xbd800000,
0x3d800000,0x3d6dbcc4,0x3d35bd35,0x3cc4bd6d,0xbd7b3c48,0xbd553d0e,0xbd0e3d55,0xbc483d7b,0x80003d80,0x3cc43d6d,0x3d353d35,0x3d6d3cc4,0xbc48bd7b,0xbd0ebd55,0xbd55bd0e,0xbd7bbc48,
0xbd800000,0xbd6d3cc4,0xbd353d35,0xbcc43d6d,0x3d7bbc48,0x3d55bd0e,0x3d0ebd55,0x3c48bd7b,0x8000bd80,0xbcc4bd6d,0xbd35bd35,0xbd6dbcc4,0x3c483d7b,0x3d0e3d55,0x3d553d0e,0x3d7b3c48,
0xbd0e3d55,0x3d7b3c48,0xbc48bd7b,0xbd553d0e,0x3d800000,0xbcc4bd6d,0xbd353d35,0x3d6d3cc4,0xbd55bd0e,0xbc483d7b,0x3d7bbc48,0xbd0ebd55,0x80003d80,0x3d6dbcc4,0xbd35bd35,0xbcc43d6d,
0x3d0ebd55,0xbd7bbc48,0x3c483d7b,0x3d55bd0e,0xbd800000,0x3cc43d6d,0x3d35bd35,0xbd6dbcc4,0x3d553d0e,0x3c48bd7b,0xbd7b3c48,0x3d0e3d55,0x8000bd80,0xbd6d3cc4,0x3d353d35,0x3cc4bd6d,
0x80003d80,0x3d353d35,0x3d800000,0x3d35bd35,0xbcc4bd6d,0xbd6dbcc4,0xbd6d3cc4,0xbcc43d6d,0x8000bd80,0xbd35bd35,0xbd800000,0xbd353d35,0x3cc43d6d,0x3d6d3cc4,0x3d6dbcc4,0x3cc4bd6d,
0x80003d80,0x3d353d35,0x3d800000,0x3d35bd35,0xbcc4bd6d,0xbd6dbcc4,0xbd6d3cc4,0xbcc43d6d,0x8000bd80,0xbd35bd35,0xbd800000,0xbd353d35,0x3cc43d6d,0x3d6d3cc4,0x3d6dbcc4,0x3cc4bd6d,
0xbd6dbcc4,0x3cc43d6d,0x3cc4bd6d,0xbd6d3cc4,0x80003d80,0x3d35bd35,0xbd800000,0x3d353d35,0x3d6d3cc4,0xbcc4bd6d,0xbcc43d6d,0x3d6dbcc4,0x8000bd80,0xbd353d35,0x3d800000,0xbd35bd35,
0xbd6dbcc4,0x3cc43d6d,0x3cc4bd6d,0xbd6d3cc4,0x80003d80,0x3d35bd35,0xbd800000,0x3d353d35,0x3d6d3cc4,0xbcc4bd6d,0xbcc43d6d,0x3d6dbcc4,0x8000bd80,0xbd353d35,0x3d800000,0xbd35bd35,
0x3d800000,0x3cc4bd6d,0xbd35bd35,0xbd6d3cc4,0xbd553d0e,0x3c483d7b,0x3d7b3c48,0x3d0ebd55,0x8000bd80,0xbd6dbcc4,0xbd353d35,0x3cc43d6d,0x3d0e3d55,0x3d7bbc48,0x3c48bd7b,0xbd55bd0e,
0xbd800000,0xbcc43d6d,0x3d353d35,0x3d6dbcc4,0x3d55bd0e,0xbc48bd7b,0xbd7bbc48,0xbd0e3d55,0x80003d80,0x3d6d3cc4,0x3d35bd35,0xbcc4bd6d,0xbd0ebd55,0xbd7b3c48,0xbc483d7b,0x3d553d0e,
0xbc483d7b,0x3d0ebd55,0xbd553d0e,0x3d7bbc48,0x3d800000,0xbd6dbcc4,0x3d353d35,0xbcc4bd6d,0x3d7b3c48,0xbd55bd0e,0x3d0e3d55,0xbc48bd7b,0x8000bd80,0xbcc43d6d,0x3d35bd35,0xbd6d3cc4,
0x3c48bd7b,0xbd0e3d55,0x3d55bd0e,0xbd7b3c48,0xbd800000,0x3d6d3cc4,0xbd35bd35,0x3cc43d6d,0xbd7bbc48,0x3d553d0e,0xbd0ebd55,0x3c483d7b,0x80003d80,0x3cc4bd6d,0xbd353d35,0x3d6dbcc4,
0x3d800000,0x3d800000,0x3d800000,0x3d800000,0xbd800000,0xbd800000,0xbd800000,0xbd800000,0x3d800000,0x3d800000,0x3d800000,0x3d800000,0xbd800000,0xbd800000,0xbd800000,0xbd800000,
0x3d800000,0x3d800000,0x3d800000,0x3d800000,0xbd800000,0xbd800000,0xbd800000,0xbd800000,0x3d800000,0x3d800000,0x3d800000,0x3d800000,0xbd800000,0xbd800000,0xbd800000,0xbd800000,
0xbd353d35,0x3d353d35,0x3d35bd35,0xbd35bd35,0x3d800000,0xbd80,0xbd800000,0x3d80,0xbd353d35,0x3d353d35,0x3d35bd35,0xbd35bd35,0x3d800000,0xbd80,0xbd800000,0x3d80,
0xbd353d35,0x3d353d35,0x3d35bd35,0xbd35bd35,0x3d800000,0xbd80,0xbd800000,0x3d80,0xbd353d35,0x3d353d35,0x3d35bd35,0xbd35bd35,0x3d800000,0xbd80,0xbd800000,0x3d80,
0xbd80,0xbcc4bd6d,0xbd35bd35,0xbd6dbcc4,0x3c483d7b,0x3d0e3d55,0x3d553d0e,0x3d7b3c48,0x3d800000,0x3d6dbcc4,0x3d35bd35,0x3cc4bd6d,0xbd7b3c48,0xbd553d0e,0xbd0e3d55,0xbc483d7b,
0x3d80,0x3cc43d6d,0x3d353d35,0x3d6d3cc4,0xbc48bd7b,0xbd0ebd55,0xbd55bd0e,0xbd7bbc48,0xbd800000,0xbd6d3cc4,0xbd353d35,0xbcc43d6d,0x3d7bbc48,0x3d55bd0e,0x3d0ebd55,0x3c48bd7b,
0x3d553d0e,0x3c48bd7b,0xbd7b3c48,0x3d0e3d55,0xbd80,0xbd6d3cc4,0x3d353d35,0x3cc4bd6d,0xbd0e3d55,0x3d7b3c48,0xbc48bd7b,0xbd553d0e,0x3d800000,0xbcc4bd6d,0xbd353d35,0x3d6d3cc4,
0xbd55bd0e,0xbc483d7b,0x3d7bbc48,0xbd0ebd55,0x3d80,0x3d6dbcc4,0xbd35bd35,0xbcc43d6d,0x3d0ebd55,0xbd7bbc48,0x3c483d7b,0x3d55bd0e,0xbd800000,0x3cc43d6d,0x3d35bd35,0xbd6dbcc4,
0x3d800000,0x3d35bd35,0xbd80,0xbd35bd35,0xbd6d3cc4,0xbcc43d6d,0x3cc43d6d,0x3d6d3cc4,0xbd800000,0xbd353d35,0x3d80,0x3d353d35,0x3d6dbcc4,0x3cc4bd6d,0xbcc4bd6d,0xbd6dbcc4,
0x3d800000,0x3d35bd35,0xbd80,0xbd35bd35,0xbd6d3cc4,0xbcc43d6d,0x3cc43d6d,0x3d6d3cc4,0xbd800000,0xbd353d35,0x3d80,0x3d353d35,0x3d6dbcc4,0x3cc4bd6d,0xbcc4bd6d,0xbd6dbcc4,
0xbcc43d6d,0x3d6dbcc4,0xbd6dbcc4,0x3cc43d6d,0x3d800000,0xbd35bd35,0x3d80,0x3d35bd35,0x3cc4bd6d,0xbd6d3cc4,0x3d6d3cc4,0xbcc4bd6d,0xbd800000,0x3d353d35,0xbd80,0xbd353d35,
0xbcc43d6d,0x3d6dbcc4,0xbd6dbcc4,0x3cc43d6d,0x3d800000,0xbd35bd35,0x3d80,0x3d35bd35,0x3cc4bd6d,0xbd6d3cc4,0x3d6d3cc4,0xbcc4bd6d,0xbd800000,0x3d353d35,0xbd80,0xbd353d35,
0xbd80,0xbd6dbcc4,0xbd353d35,0x3cc43d6d,0x3d0e3d55,0x3d7bbc48,0x3c48bd7b,0xbd55bd0e,0xbd800000,0xbcc43d6d,0x3d353d35,0x3d6dbcc4,0x3d55bd0e,0xbc48bd7b,0xbd7bbc48,0xbd0e3d55,
0x3d80,0x3d6d3cc4,0x3d35bd35,0xbcc4bd6d,0xbd0ebd55,0xbd7b3c48,0xbc483d7b,0x3d553d0e,0x3d800000,0x3cc4bd6d,0xbd35bd35,0xbd6d3cc4,0xbd553d0e,0x3c483d7b,0x3d7b3c48,0x3d0ebd55,
0x3d7b3c48,0xbd55bd0e,0x3d0e3d55,0xbc48bd7b,0xbd80,0xbcc43d6d,0x3d35bd35,0xbd6d3cc4,0x3c48bd7b,0xbd0e3d55,0x3d55bd0e,0xbd7b3c48,0xbd800000,0x3d6d3cc4,0xbd35bd35,0x3cc43d6d,
0xbd7bbc48,0x3d553d0e,0xbd0ebd55,0x3c483d7b,0x3d80,0x3cc4bd6d,0xbd353d35,0x3d6dbcc4,0xbc483d7b,0x3d0ebd55,0xbd553d0e,0x3d7bbc48,0x3d800000,0xbd6dbcc4,0x3d353d35,0xbcc4bd6d,
0x80003d80,0x8000bd80,0x80003d80,0x8000bd80,0xbd800000,0x3d800000,0xbd800000,0x3d800000,0x80003d80,0x8000bd80,0x80003d80,0x8000bd80,0xbd800000,0x3d800000,0xbd800000,0x3d800000,
0x80003d80,0x8000bd80,0x80003d80,0x8000bd80,0xbd800000,0x3d800000,0xbd800000,0x3d800000,0x80003d80,0x8000bd80,0x80003d80,0x8000bd80,0xbd800000,0x3d800000,0xbd800000,0x3d800000,
0xbd353d35,0xbd35bd35,0x3d35bd35,0x3d353d35,0x80003d80,0xbd800000,0x8000bd80,0x3d800000,0xbd353d35,0xbd35bd35,0x3d35bd35,0x3d353d35,0x80003d80,0xbd800000,0x8000bd80,0x3d800000,
0xbd353d35,0xbd35bd35,0x3d35bd35,0x3d353d35,0x80003d80,0xbd800000,0x8000bd80,0x3d800000,0xbd353d35,0xbd35bd35,0x3d35bd35,0x3d353d35,0x80003d80,0xbd800000,0x8000bd80,0x3d800000,
0x3d800000,0xbd6d3cc4,0x3d35bd35,0xbcc43d6d,0x3c483d7b,0xbd0ebd55,0x3d553d0e,0xbd7bbc48,0x80003d80,0xbcc4bd6d,0x3d353d35,0xbd6dbcc4,0xbd7b3c48,0x3d55bd0e,0xbd0e3d55,0x3c48bd7b,
0xbd800000,0x3d6dbcc4,0xbd353d35,0x3cc4bd6d,0xbc48bd7b,0x3d0e3d55,0xbd55bd0e,0x3d7b3c48,0x8000bd80,0x3cc43d6d,0xbd35bd35,0x3d6d3cc4,0x3d7bbc48,0xbd553d0e,0x3d0ebd55,0xbc483d7b,
0x3d553d0e,0xbc483d7b,0xbd7b3c48,0xbd0ebd55,0x3d800000,0x3cc43d6d,0xbd353d35,0xbd6dbcc4,0xbd0e3d55,0xbd7bbc48,0xbc48bd7b,0x3d55bd0e,0x80003d80,0xbd6d3cc4,0xbd35bd35,0x3cc4bd6d,
0xbd55bd0e,0x3c48bd7b,0x3d7bbc48,0x3d0e3d55,0xbd800000,0xbcc4bd6d,0x3d35bd35,0x3d6d3cc4,0x3d0ebd55,0x3d7b3c48,0x3c483d7b,0xbd553d0e,0x8000bd80,0x3d6dbcc4,0x3d353d35,0xbcc43d6d,
0x80003d80,0xbd35bd35,0x3d800000,0xbd353d35,0xbd6d3cc4,0x3cc4bd6d,0x3cc43d6d,0xbd6dbcc4,0x8000bd80,0x3d353d35,0xbd800000,0x3d35bd35,0x3d6dbcc4,0xbcc43d6d,0xbcc4bd6d,0x3d6d3cc4,
0x80003d80,0xbd35bd35,0x3d800000,0xbd353d35,0xbd6d3cc4,0x3cc4bd6d,0x3cc43d6d,0xbd6dbcc4,0x8000bd80,0x3d353d35,0xbd800000,0x3d35bd35,0x3d6dbcc4,0xbcc43d6d,0xbcc4bd6d,0x3d6d3cc4,
0xbcc43d6d,0xbd6d3cc4,0xbd6dbcc4,0xbcc4bd6d,0x80003d80,0xbd353d35,0xbd800000,0xbd35bd35,0x3cc4bd6d,0x3d6dbcc4,0x3d6d3cc4,0x3cc43d6d,0x8000bd80,0x3d35bd35,0x3d800000,0x3d353d35,
0xbcc43d6d,0xbd6d3cc4,0xbd6dbcc4,0xbcc4bd6d,0x80003d80,0xbd353d35,0xbd800000,0xbd35bd35,0x3cc4bd6d,0x3d6dbcc4,0x3d6d3cc4,0x3cc43d6d,0x8000bd80,0x3d35bd35,0x3d800000,0x3d353d35,
0x3d800000,0xbcc43d6d,0xbd35bd35,0x3d6dbcc4,0x3d0e3d55,0xbd7b3c48,0x3c48bd7b,0x3d553d0e,0x8000bd80,0x3d6d3cc4,0xbd353d35,0xbcc4bd6d,0x3d55bd0e,0x3c483d7b,0xbd7bbc48,0x3d0ebd55,
0xbd800000,0x3cc4bd6d,0x3d353d35,0xbd6d3cc4,0xbd0ebd55,0x3d7bbc48,0xbc483d7b,0xbd55bd0e,0x80003d80,0xbd6dbcc4,0x3d35bd35,0x3cc43d6d,0xbd553d0e,0xbc48bd7b,0x3d7b3c48,0xbd0e3d55,
0x3d7b3c48,0x3d553d0e,0x3d0e3d55,0x3c483d7b,0x3d800000,0x3d6d3cc4,0x3d353d35,0x3cc43d6d,0x3c48bd7b,0x3d0ebd55,0x3d55bd0e,0x3d7bbc48,0x8000bd80,0x3cc4bd6d,0x3d35bd35,0x3d6dbcc4,
0xbd7bbc48,0xbd55bd0e,0xbd0ebd55,0xbc48bd7b,0xbd800000,0xbd6dbcc4,0xbd35bd35,0xbcc4bd6d,0xbc483d7b,0xbd0e3d55,0xbd553d0e,0xbd7b3c48,0x80003d80,0xbcc43d6d,0xbd353d35,0xbd6d3cc4,
0x3d800000,0xbd800000,0x3d800000,0xbd800000,0x3d80,0xbd80,0x3d80,0xbd80,0x3d800000,0xbd800000,0x3d800000,0xbd800000,0x3d80,0xbd80,0x3d80,0xbd80,
0x3d800000,0xbd800000,0x3d800000,0xbd800000,0x3d80,0xbd80,0x3d80,0xbd80,0x3d800000,0xbd800000,0x3d800000,0xbd800000,0x3d80,0xbd80,0x3d80,0xbd80,
0x3d353d35,0xbd353d35,0xbd35bd35,0x3d35bd35,0x3d800000,0x3d80,0xbd800000,0xbd80,0x3d353d35,0xbd353d35,0xbd35bd35,0x3d35bd35,0x3d800000,0x3d80,0xbd800000,0xbd80,
0x3d353d35,0xbd353d35,0xbd35bd35,0x3d35bd35,0x3d800000,0x3d80,0xbd800000,0xbd80,0x3d353d35,0xbd353d35,0xbd35bd35,0x3d35bd35,0x3d800000,0x3d80,0xbd800000,0xbd80,
0xbd80,0x3cc43d6d,0xbd35bd35,0x3d6d3cc4,0x3d7bbc48,0xbd553d0e,0x3d0ebd55,0xbc483d7b,0x3d800000,0xbd6d3cc4,0x3d35bd35,0xbcc43d6d,0x3c483d7b,0xbd0ebd55,0x3d553d0e,0xbd7bbc48,
0x3d80,0xbcc4bd6d,0x3d353d35,0xbd6dbcc4,0xbd7b3c48,0x3d55bd0e,0xbd0e3d55,0x3c48bd7b,0xbd800000,0x3d6dbcc4,0xbd353d35,0x3cc4bd6d,0xbc48bd7b,0x3d0e3d55,0xbd55bd0e,0x3d7b3c48,
0x3d0ebd55,0x3d7b3c48,0x3c483d7b,0xbd553d0e,0xbd80,0x3d6dbcc4,0x3d353d35,0xbcc43d6d,0x3d553d0e,0xbc483d7b,0xbd7b3c48,0xbd0ebd55,0x3d800000,0x3cc43d6d,0xbd353d35,0xbd6dbcc4,
0xbd0e3d55,0xbd7bbc48,0xbc48bd7b,0x3d55bd0e,0x3d80,0xbd6d3cc4,0xbd35bd35,0x3cc4bd6d,0xbd55bd0e,0x3c48bd7b,0x3d7bbc48,0x3d0e3d55,0xbd800000,0xbcc4bd6d,0x3d35bd35,0x3d6d3cc4,
0x3d800000,0xbd353d35,0xbd80,0x3d353d35,0x3cc43d6d,0xbd6dbcc4,0x3d6dbcc4,0xbcc43d6d,0xbd800000,0x3d35bd35,0x3d80,0xbd35bd35,0xbcc4bd6d,0x3d6d3cc4,0xbd6d3cc4,0x3cc4bd6d,
0x3d800000,0xbd353d35,0xbd80,0x3d353d35,0x3cc43d6d,0xbd6dbcc4,0x3d6dbcc4,0xbcc43d6d,0xbd800000,0x3d35bd35,0x3d80,0xbd35bd35,0xbcc4bd6d,0x3d6d3cc4,0xbd6d3cc4,0x3cc4bd6d,
0x3d6d3cc4,0x3cc43d6d,0xbcc43d6d,0xbd6d3cc4,0x3d800000,0x3d353d35,0x3d80,0xbd353d35,0xbd6dbcc4,0xbcc4bd6d,0x3cc4bd6d,0x3d6dbcc4,0xbd800000,0xbd35bd35,0xbd80,0x3d35bd35,
0x3d6d3cc4,0x3cc43d6d,0xbcc43d6d,0xbd6d3cc4,0x3d800000,0x3d353d35,0x3d80,0xbd353d35,0xbd6dbcc4,0xbcc4bd6d,0x3cc4bd6d,0x3d6dbcc4,0xbd800000,0xbd35bd35,0xbd80,0x3d35bd35,
0xbd80,0x3d6d3cc4,0xbd353d35,0xbcc4bd6d,0x3d55bd0e,0x3c483d7b,0xbd7bbc48,0x3d0ebd55,0xbd800000,0x3cc4bd6d,0x3d353d35,0xbd6d3cc4,0xbd0ebd55,0x3d7bbc48,0xbc483d7b,0xbd55bd0e,
0x3d80,0xbd6dbcc4,0x3d35bd35,0x3cc43d6d,0xbd553d0e,0xbc48bd7b,0x3d7b3c48,0xbd0e3d55,0x3d800000,0xbcc43d6d,0xbd35bd35,0x3d6dbcc4,0x3d0e3d55,0xbd7b3c48,0x3c48bd7b,0x3d553d0e,
0x3c48bd7b,0x3d0ebd55,0x3d55bd0e,0x3d7bbc48,0xbd80,0x3cc4bd6d,0x3d35bd35,0x3d6dbcc4,0xbd7bbc48,0xbd55bd0e,0xbd0ebd55,0xbc48bd7b,0xbd800000,0xbd6dbcc4,0xbd35bd35,0xbcc4bd6d,
0xbc483d7b,0xbd0e3d55,0xbd553d0e,0xbd7b3c48,0x3d80,0xbcc43d6d,0xbd353d35,0xbd6d3cc4,0x3d7b3c48,0x3d553d0e,0x3d0e3d55,0x3c483d7b,0x3d800000,0x3d6d3cc4,0x3d353d35,0x3cc43d6d,
0x3d80,0x3d80,0x3d80,0x3d80,0x3d80,0x3d80,0x3d80,0x3d80,0x3d80,0x3d80,0x3d80,0x3d80,0x3d80,0x3d80,0x3d80,0x3d80,
0x3d80,0x3d80,0x3d80,0x3d80,0x3d80,0x3d80,0x3d80,0x3d80,0x3d80,0x3d80,0x3d80,0x3d80,0x3d80,0x3d80,0x3d80,0x3d80,
0xbd353d35,0xbd553d0e,0xbd6d3cc4,0xbd7b3c48,0x3d80,0xbc483d7b,0xbcc43d6d,0xbd0e3d55,0xbd35bd35,0xbd0ebd55,0xbcc4bd6d,0xbc48bd7b,0xbd800000,0xbd7bbc48,0xbd6dbcc4,0xbd55bd0e,
0x3d35bd35,0x3d55bd0e,0x3d6dbcc4,0x3d7bbc48,0xbd80,0x3c48bd7b,0x3cc4bd6d,0x3d0ebd55,0x3d353d35,0x3d0e3d55,0x3cc43d6d,0x3c483d7b,0x3d800000,0x3d7b3c48,0x3d6d3cc4,0x3d553d0e,
0xbd80,0x3cc4bd6d,0x3d35bd35,0x3d6dbcc4,0x3d800000,0x3d6d3cc4,0x3d353d35,0x3cc43d6d,0x3d80,0xbcc43d6d,0xbd353d35,0xbd6d3cc4,0xbd800000,0xbd6dbcc4,0xbd35bd35,0xbcc4bd6d,
0xbd80,0x3cc4bd6d,0x3d35bd35,0x3d6dbcc4,0x3d800000,0x3d6d3cc4,0x3d353d35,0x3cc43d6d,0x3d80,0xbcc43d6d,0xbd353d35,0xbd6d3cc4,0xbd800000,0xbd6dbcc4,0xbd35bd35,0xbcc4bd6d,
0xbd353d35,0xbd7b3c48,0xbd6dbcc4,0xbd0ebd55,0x3d800000,0x3d553d0e,0x3cc43d6d,0xbc483d7b,0xbd35bd35,0xbc48bd7b,0x3cc4bd6d,0x3d55bd0e,0x3d80,0xbd0e3d55,0xbd6d3cc4,0xbd7bbc48,
0x3d35bd35,0x3d7bbc48,0x3d6d3cc4,0x3d0e3d55,0xbd800000,0xbd55bd0e,0xbcc4bd6d,0x3c48bd7b,0x3d353d35,0x3c483d7b,0xbcc43d6d,0xbd553d0e,0xbd80,0x3d0ebd55,0x3d6dbcc4,0x3d7b3c48,
0x3d80,0xbd353d35,0xbd800000,0xbd35bd35,0xbd80,0x3d35bd35,0x3d800000,0x3d353d35,0x3d80,0xbd353d35,0xbd800000,0xbd35bd35,0xbd80,0x3d35bd35,0x3d800000,0x3d353d35,
0x3d80,0xbd353d35,0xbd800000,0xbd35bd35,0xbd80,0x3d35bd35,0x3d800000,0x3d353d35,0x3d80,0xbd353d35,0xbd800000,0xbd35bd35,0xbd80,0x3d35bd35,0x3d800000,0x3d353d35,
0xbd353d35,0xbd7bbc48,0xbcc4bd6d,0x3d0ebd55,0xbd80,0x3d55bd0e,0x3d6d3cc4,0x3c483d7b,0xbd35bd35,0x3c48bd7b,0x3d6dbcc4,0x3d553d0e,0x3d800000,0x3d0e3d55,0xbcc43d6d,0xbd7b3c48,
0x3d35bd35,0x3d7b3c48,0x3cc43d6d,0xbd0e3d55,0x3d80,0xbd553d0e,0xbd6dbcc4,0xbc48bd7b,0x3d353d35,0xbc483d7b,0xbd6d3cc4,0xbd55bd0e,0xbd800000,0xbd0ebd55,0x3cc4bd6d,0x3d7bbc48,
0xbd80,0x3d6dbcc4,0x3d353d35,0xbcc43d6d,0xbd800000,0xbcc4bd6d,0x3d35bd35,0x3d6d3cc4,0x3d80,0xbd6d3cc4,0xbd35bd35,0x3cc4bd6d,0x3d800000,0x3cc43d6d,0xbd353d35,0xbd6dbcc4,
0xbd80,0x3d6dbcc4,0x3d353d35,0xbcc43d6d,0xbd800000,0xbcc4bd6d,0x3d35bd35,0x3d6d3cc4,0x3d80,0xbd6d3cc4,0xbd35bd35,0x3cc4bd6d,0x3d800000,0x3cc43d6d,0xbd353d35,0xbd6dbcc4,
0xbd353d35,0xbd55bd0e,0x3cc4bd6d,0x3d7b3c48,0xbd800000,0xbc48bd7b,0x3d6dbcc4,0x3d0e3d55,0xbd35bd35,0x3d0ebd55,0x3d6d3cc4,0xbc483d7b,0xbd80,0x3d7bbc48,0x3cc43d6d,0xbd553d0e,
0x3d35bd35,0x3d553d0e,0xbcc43d6d,0xbd7bbc48,0x3d800000,0x3c483d7b,0xbd6d3cc4,0xbd0ebd55,0x3d353d35,0xbd0e3d55,0xbd6dbcc4,0x3c48bd7b,0x3d80,0xbd7b3c48,0xbcc4bd6d,0x3d55bd0e,
0xbd800000,0xbd800000,0xbd800000,0xbd800000,0xbd800000,0xbd800000,0xbd800000,0xbd800000,0xbd800000,0xbd800000,0xbd800000,0xbd800000,0xbd800000,0xbd800000,0xbd800000,0xbd800000,
0xbd800000,0xbd800000,0xbd800000,0xbd800000,0xbd800000,0xbd800000,0xbd800000,0xbd800000,0xbd800000,0xbd800000,0xbd800000,0xbd800000,0xbd800000,0xbd800000,0xbd800000,0xbd800000,
0xbd35bd35,0xbd0ebd55,0xbcc4bd6d,0xbc48bd7b,0xbd800000,0xbd7bbc48,0xbd6dbcc4,0xbd55bd0e,0x3d35bd35,0x3d55bd0e,0x3d6dbcc4,0x3d7bbc48,0x8000bd80,0x3c48bd7b,0x3cc4bd6d,0x3d0ebd55,
0x3d353d35,0x3d0e3d55,0x3cc43d6d,0x3c483d7b,0x3d800000,0x3d7b3c48,0x3d6d3cc4,0x3d553d0e,0xbd353d35,0xbd553d0e,0xbd6d3cc4,0xbd7b3c48,0x80003d80,0xbc483d7b,0xbcc43d6d,0xbd0e3d55,
0x3d800000,0x3d6d3cc4,0x3d353d35,0x3cc43d6d,0x80003d80,0xbcc43d6d,0xbd353d35,0xbd6d3cc4,0xbd800000,0xbd6dbcc4,0xbd35bd35,0xbcc4bd6d,0x8000bd80,0x3cc4bd6d,0x3d35bd35,0x3d6dbcc4,
0x3d800000,0x3d6d3cc4,0x3d353d35,0x3cc43d6d,0x80003d80,0xbcc43d6d,0xbd353d35,0xbd6d3cc4,0xbd800000,0xbd6dbcc4,0xbd35bd35,0xbcc4bd6d,0x8000bd80,0x3cc4bd6d,0x3d35bd35,0x3d6dbcc4,
0xbd35bd35,0xbc48bd7b,0x3cc4bd6d,0x3d55bd0e,0x80003d80,0xbd0e3d55,0xbd6d3cc4,0xbd7bbc48,0x3d35bd35,0x3d7bbc48,0x3d6d3cc4,0x3d0e3d55,0xbd800000,0xbd55bd0e,0xbcc4bd6d,0x3c48bd7b,
0x3d353d35,0x3c483d7b,0xbcc43d6d,0xbd553d0e,0x8000bd80,0x3d0ebd55,0x3d6dbcc4,0x3d7b3c48,0xbd353d35,0xbd7b3c48,0xbd6dbcc4,0xbd0ebd55,0x3d800000,0x3d553d0e,0x3cc43d6d,0xbc483d7b,
0xbd800000,0xbd35bd35,0x8000bd80,0x3d35bd35,0x3d800000,0x3d353d35,0x80003d80,0xbd353d35,0xbd800000,0xbd35bd35,0x8000bd80,0x3d35bd35,0x3d800000,0x3d353d35,0x80003d80,0xbd353d35,
0xbd800000,0xbd35bd35,0x8000bd80,0x3d35bd35,0x3d800000,0x3d353d35,0x80003d80,0xbd353d35,0xbd800000,0xbd35bd35,0x8000bd80,0x3d35bd35,0x3d800000,0x3d353d35,0x80003d80,0xbd353d35,
0xbd35bd35,0x3c48bd7b,0x3d6dbcc4,0x3d553d0e,0x3d800000,0x3d0e3d55,0xbcc43d6d,0xbd7b3c48,0x3d35bd35,0x3d7b3c48,0x3cc43d6d,0xbd0e3d55,0x80003d80,0xbd553d0e,0xbd6dbcc4,0xbc48bd7b,
0x3d353d35,0xbc483d7b,0xbd6d3cc4,0xbd55bd0e,0xbd800000,0xbd0ebd55,0x3cc4bd6d,0x3d7bbc48,0xbd353d35,0xbd7bbc48,0xbcc4bd6d,0x3d0ebd55,0x8000bd80,0x3d55bd0e,0x3d6d3cc4,0x3c483d7b,
0x3d800000,0x3cc43d6d,0xbd353d35,0xbd6dbcc4,0x8000bd80,0x3d6dbcc4,0x3d353d35,0xbcc43d6d,0xbd800000,0xbcc4bd6d,0x3d35bd35,0x3d6d3cc4,0x80003d80,0xbd6d3cc4,0xbd35bd35,0x3cc4bd6d,
0x3d800000,0x3cc43d6d,0xbd353d35,0xbd6dbcc4,0x8000bd80,0x3d6dbcc4,0x3d353d35,0xbcc43d6d,0xbd800000,0xbcc4bd6d,0x3d35bd35,0x3d6d3cc4,0x80003d80,0xbd6d3cc4,0xbd35bd35,0x3cc4bd6d,
0xbd35bd35,0x3d0ebd55,0x3d6d3cc4,0xbc483d7b,0x8000bd80,0x3d7bbc48,0x3cc43d6d,0xbd553d0e,0x3d35bd35,0x3d553d0e,0xbcc43d6d,0xbd7bbc48,0x3d800000,0x3c483d7b,0xbd6d3cc4,0xbd0ebd55,
0x3d353d35,0xbd0e3d55,0xbd6dbcc4,0x3c48bd7b,0x80003d80,0xbd7b3c48,0xbcc4bd6d,0x3d55bd0e,0xbd353d35,0xbd55bd0e,0x3cc4bd6d,0x3d7b3c48,0xbd800000,0xbc48bd7b,0x3d6dbcc4,0x3d0e3d55,
0x3d80,0xbd800000,0xbd80,0x3d800000,0x3d80,0xbd800000,0xbd80,0x3d800000,0x3d80,0xbd800000,0xbd80,0x3d800000,0x3d80,0xbd800000,0xbd80,0x3d800000,
0x3d80,0xbd800000,0xbd80,0x3d800000,0x3d80,0xbd800000,0xbd80,0x3d800000,0x3d80,0xbd800000,0xbd80,0x3d800000,0x3d80,0xbd800000,0xbd80,0x3d800000,
0xbd353d35,0xbd0ebd55,0x3d6dbcc4,0x3c483d7b,0x3d80,0xbd7bbc48,0x3cc4bd6d,0x3d553d0e,0xbd35bd35,0x3d55bd0e,0x3cc43d6d,0xbd7b3c48,0xbd800000,0x3c48bd7b,0x3d6d3cc4,0xbd0e3d55,
0x3d35bd35,0x3d0e3d55,0xbd6d3cc4,0xbc48bd7b,0xbd80,0x3d7b3c48,0xbcc43d6d,0xbd55bd0e,0x3d353d35,0xbd553d0e,0xbcc4bd6d,0x3d7bbc48,0x3d800000,0xbc483d7b,0xbd6dbcc4,0x3d0ebd55,
0xbd80,0x3d6d3cc4,0xbd353d35,0xbcc4bd6d,0x3d800000,0xbcc43d6d,0xbd35bd35,0x3d6dbcc4,0x3d80,0xbd6dbcc4,0x3d35bd35,0x3cc43d6d,0xbd800000,0x3cc4bd6d,0x3d353d35,0xbd6d3cc4,
0xbd80,0x3d6d3cc4,0xbd353d35,0xbcc4bd6d,0x3d800000,0xbcc43d6d,0xbd35bd35,0x3d6dbcc4,0x3d80,0xbd6dbcc4,0x3d35bd35,0x3cc43d6d,0xbd800000,0x3cc4bd6d,0x3d353d35,0xbd6d3cc4,
0xbd353d35,0xbc48bd7b,0x3d6d3cc4,0xbd553d0e,0x3d800000,0xbd0e3d55,0xbcc4bd6d,0x3d7b3c48,0xbd35bd35,0x3d7bbc48,0xbcc43d6d,0xbd0ebd55,0x3d80,0xbd55bd0e,0x3d6dbcc4,0xbc483d7b,
0x3d35bd35,0x3c483d7b,0xbd6dbcc4,0x3d55bd0e,0xbd800000,0x3d0ebd55,0x3cc43d6d,0xbd7bbc48,0x3d353d35,0xbd7b3c48,0x3cc4bd6d,0x3d0e3d55,0xbd80,0x3d553d0e,0xbd6d3cc4,0x3c48bd7b,
0x3d80,0xbd35bd35,0x3d800000,0xbd353d35,0xbd80,0x3d353d35,0xbd800000,0x3d35bd35,0x3d80,0xbd35bd35,0x3d800000,0xbd353d35,0xbd80,0x3d353d35,0xbd800000,0x3d35bd35,
0x3d80,0xbd35bd35,0x3d800000,0xbd353d35,0xbd80,0x3d353d35,0xbd800000,0x3d35bd35,0x3d80,0xbd35bd35,0x3d800000,0xbd353d35,0xbd80,0x3d353d35,0xbd800000,0x3d35bd35,
0xbd353d35,0x3c48bd7b,0x3cc43d6d,0xbd55bd0e,0xbd80,0x3d0e3d55,0xbd6dbcc4,0x3d7bbc48,0xbd35bd35,0x3d7b3c48,0xbd6d3cc4,0x3d0ebd55,0x3d800000,0xbd553d0e,0x3cc4bd6d,0x3c483d7b,
0x3d35bd35,0xbc483d7b,0xbcc4bd6d,0x3d553d0e,0x3d80,0xbd0ebd55,0x3d6d3cc4,0xbd7b3c48,0x3d353d35,0xbd7bbc48,0x3d6dbcc4,0xbd0e3d55,0xbd800000,0x3d55bd0e,0xbcc43d6d,0xbc48bd7b,
0xbd80,0x3cc43d6d,0xbd35bd35,0x3d6d3cc4,0xbd800000,0x3d6dbcc4,0xbd353d35,0x3cc4bd6d,0x3d80,0xbcc4bd6d,0x3d353d35,0xbd6dbcc4,0x3d800000,0xbd6d3cc4,0x3d35bd35,0xbcc43d6d,
0xbd80,0x3cc43d6d,0xbd35bd35,0x3d6d3cc4,0xbd800000,0x3d6dbcc4,0xbd353d35,0x3cc4bd6d,0x3d80,0xbcc4bd6d,0x3d353d35,0xbd6dbcc4,0x3d800000,0xbd6d3cc4,0x3d35bd35,0xbcc43d6d,
0xbd353d35,0x3d0ebd55,0xbcc43d6d,0x3c48bd7b,0xbd800000,0x3d7bbc48,0xbd6d3cc4,0x3d55bd0e,0xbd35bd35,0x3d553d0e,0xbd6dbcc4,0x3d7b3c48,0xbd80,0x3c483d7b,0xbcc4bd6d,0x3d0e3d55,
0x3d35bd35,0xbd0e3d55,0x3cc4bd6d,0xbc483d7b,0x3d800000,0xbd7b3c48,0x3d6dbcc4,0xbd553d0e,0x3d353d35,0xbd55bd0e,0x3d6d3cc4,0xbd7bbc48,0x3d80,0xbc48bd7b,0x3cc43d6d,0xbd0ebd55,
0xbd800000,0x8000bd80,0x3d800000,0x80003d80,0xbd800000,0x8000bd80,0x3d800000,0x80003d80,0xbd800000,0x8000bd80,0x3d800000,0x80003d80,0xbd800000,0x8000bd80,0x3d800000,0x80003d80,
0xbd800000,0x8000bd80,0x3d800000,0x80003d80,0xbd800000,0x8000bd80,0x3d800000,0x80003d80,0xbd800000,0x8000bd80,0x3d800000,0x80003d80,0xbd800000,0x8000bd80,0x3d800000,0x80003d80,
0xbd35bd35,0x3d55bd0e,0x3cc43d6d,0xbd7b3c48,0xbd800000,0x3c48bd7b,0x3d6d3cc4,0xbd0e3d55,0x3d35bd35,0x3d0e3d55,0xbd6d3cc4,0xbc48bd7b,0x8000bd80,0x3d7b3c48,0xbcc43d6d,0xbd55bd0e,
0x3d353d35,0xbd553d0e,0xbcc4bd6d,0x3d7bbc48,0x3d800000,0xbc483d7b,0xbd6dbcc4,0x3d0ebd55,0xbd353d35,0xbd0ebd55,0x3d6dbcc4,0x3c483d7b,0x80003d80,0xbd7bbc48,0x3cc4bd6d,0x3d553d0e,
0x3d800000,0xbcc43d6d,0xbd35bd35,0x3d6dbcc4,0x80003d80,0xbd6dbcc4,0x3d35bd35,0x3cc43d6d,0xbd800000,0x3cc4bd6d,0x3d353d35,0xbd6d3cc4,0x8000bd80,0x3d6d3cc4,0xbd353d35,0xbcc4bd6d,
0x3d800000,0xbcc43d6d,0xbd35bd35,0x3d6dbcc4,0x80003d80,0xbd6dbcc4,0x3d35bd35,0x3cc43d6d,0xbd800000,0x3cc4bd6d,0x3d353d35,0xbd6d3cc4,0x8000bd80,0x3d6d3cc4,0xbd353d35,0xbcc4bd6d,
0xbd35bd35,0x3d7bbc48,0xbcc43d6d,0xbd0ebd55,0x80003d80,0xbd55bd0e,0x3d6dbcc4,0xbc483d7b,0x3d35bd35,0x3c483d7b,0xbd6dbcc4,0x3d55bd0e,0xbd800000,0x3d0ebd55,0x3cc43d6d,0xbd7bbc48,
0x3d353d35,0xbd7b3c48,0x3cc4bd6d,0x3d0e3d55,0x8000bd80,0x3d553d0e,0xbd6d3cc4,0x3c48bd7b,0xbd353d35,0xbc48bd7b,0x3d6d3cc4,0xbd553d0e,0x3d800000,0xbd0e3d55,0xbcc4bd6d,0x3d7b3c48,
0xbd800000,0x3d35bd35,0x80003d80,0xbd35bd35,0x3d800000,0xbd353d35,0x8000bd80,0x3d353d35,0xbd800000,0x3d35bd35,0x80003d80,0xbd35bd35,0x3d800000,0xbd353d35,0x8000bd80,0x3d353d35,
0xbd800000,0x3d35bd35,0x80003d80,0xbd35bd35,0x3d800000,0xbd353d35,0x8000bd80,0x3d353d35,0xbd800000,0x3d35bd35,0x80003d80,0xbd35bd35,0x3d800000,0xbd353d35,0x8000bd80,0x3d353d35,
0xbd35bd35,0x3d7b3c48,0xbd6d3cc4,0x3d0ebd55,0x3d800000,0xbd553d0e,0x3cc4bd6d,0x3c483d7b,0x3d35bd35,0xbc483d7b,0xbcc4bd6d,0x3d553d0e,0x80003d80,0xbd0ebd55,0x3d6d3cc4,0xbd7b3c48,
0x3d353d35,0xbd7bbc48,0x3d6dbcc4,0xbd0e3d55,0xbd800000,0x3d55bd0e,0xbcc43d6d,0xbc48bd7b,0xbd353d35,0x3c48bd7b,0x3cc43d6d,0xbd55bd0e,0x8000bd80,0x3d0e3d55,0xbd6dbcc4,0x3d7bbc48,
0x3d800000,0xbd6d3cc4,0x3d35bd35,0xbcc43d6d,0x8000bd80,0x3cc43d6d,0xbd35bd35,0x3d6d3cc4,0xbd800000,0x3d6dbcc4,0xbd353d35,0x3cc4bd6d,0x80003d80,0xbcc4bd6d,0x3d353d35,0xbd6dbcc4,
0x3d800000,0xbd6d3cc4,0x3d35bd35,0xbcc43d6d,0x8000bd80,0x3cc43d6d,0xbd35bd35,0x3d6d3cc4,0xbd800000,0x3d6dbcc4,0xbd353d35,0x3cc4bd6d,0x80003d80,0xbcc4bd6d,0x3d353d35,0xbd6dbcc4,
0xbd35bd35,0x3d553d0e,0xbd6dbcc4,0x3d7b3c48,0x8000bd80,0x3c483d7b,0xbcc4bd6d,0x3d0e3d55,0x3d35bd35,0xbd0e3d55,0x3cc4bd6d,0xbc483d7b,0x3d800000,0xbd7b3c48,0x3d6dbcc4,0xbd553d0e,
0x3d353d35,0xbd55bd0e,0x3d6d3cc4,0xbd7bbc48,0x80003d80,0xbc48bd7b,0x3cc43d6d,0xbd0ebd55,0xbd353d35,0x3d0ebd55,0xbcc43d6d,0x3c48bd7b,0xbd800000,0x3d7bbc48,0xbd6d3cc4,0x3d55bd0e,
0x3d80,0xbd80,0x3d80,0xbd80,0x3d80,0xbd80,0x3d80,0xbd80,0x3d80,0xbd80,0x3d80,0xbd80,0x3d80,0xbd80,0x3d80,0xbd80,
0x3d80,0xbd80,0x3d80,0xbd80,0x3d80,0xbd80,0x3d80,0xbd80,0x3d80,0xbd80,0x3d80,0xbd80,0x3d80,0xbd80,0x3d80,0xbd80,
0xbd353d35,0x3d55bd0e,0xbd6d3cc4,0x3d7bbc48,0x3d80,0x3c48bd7b,0xbcc43d6d,0x3d0ebd55,0xbd35bd35,0x3d0e3d55,0xbcc4bd6d,0x3c483d7b,0xbd800000,0x3d7b3c48,0xbd6dbcc4,0x3d553d0e,
0x3d35bd35,0xbd553d0e,0x3d6dbcc4,0xbd7b3c48,0xbd80,0xbc483d7b,0x3cc4bd6d,0xbd0e3d55,0x3d353d35,0xbd0ebd55,0x3cc43d6d,0xbc48bd7b,0x3d800000,0xbd7bbc48,0x3d6d3cc4,0xbd55bd0e,
0xbd80,0xbcc43d6d,0x3d35bd35,0xbd6d3cc4,0x3d800000,0xbd6dbcc4,0x3d353d35,0xbcc4bd6d,0x3d80,0x3cc4bd6d,0xbd353d35,0x3d6dbcc4,0xbd800000,0x3d6d3cc4,0xbd35bd35,0x3cc43d6d,
0xbd80,0xbcc43d6d,0x3d35bd35,0xbd6d3cc4,0x3d800000,0xbd6dbcc4,0x3d353d35,0xbcc4bd6d,0x3d80,0x3cc4bd6d,0xbd353d35,0x3d6dbcc4,0xbd800000,0x3d6d3cc4,0xbd35bd35,0x3cc43d6d,
0xbd353d35,0x3d7bbc48,0xbd6dbcc4,0x3d0e3d55,0x3d800000,0xbd55bd0e,0x3cc43d6d,0x3c48bd7b,0xbd35bd35,0x3c483d7b,0x3cc4bd6d,0xbd553d0e,0x3d80,0x3d0ebd55,0xbd6d3cc4,0x3d7b3c48,
0x3d35bd35,0xbd7b3c48,0x3d6d3cc4,0xbd0ebd55,0xbd800000,0x3d553d0e,0xbcc4bd6d,0xbc483d7b,0x3d353d35,0xbc48bd7b,0xbcc43d6d,0x3d55bd0e,0xbd80,0xbd0e3d55,0x3d6dbcc4,0xbd7bbc48,
0x3d80,0x3d35bd35,0xbd800000,0x3d353d35,0xbd80,0xbd353d35,0x3d800000,0xbd35bd35,0x3d80,0x3d35bd35,0xbd800000,0x3d353d35,0xbd80,0xbd353d35,0x3d800000,0xbd35bd35,
0x3d80,0x3d35bd35,0xbd800000,0x3d353d35,0xbd80,0xbd353d35,0x3d800000,0xbd35bd35,0x3d80,0x3d35bd35,0xbd800000,0x3d353d35,0xbd80,0xbd353d35,0x3d800000,0xbd35bd35,
0xbd353d35,0x3d7b3c48,0xbcc4bd6d,0xbd0e3d55,0xbd80,0xbd553d0e,0x3d6d3cc4,0xbc48bd7b,0xbd35bd35,0xbc483d7b,0x3d6dbcc4,0xbd55bd0e,0x3d800000,0xbd0ebd55,0xbcc43d6d,0x3d7bbc48,
0x3d35bd35,0xbd7bbc48,0x3cc43d6d,0x3d0ebd55,0x3d80,0x3d55bd0e,0xbd6dbcc4,0x3c483d7b,0x3d353d35,0x3c48bd7b,0xbd6d3cc4,0x3d553d0e,0xbd800000,0x3d0e3d55,0x3cc4bd6d,0xbd7b3c48,
0xbd80,0xbd6d3cc4,0x3d353d35,0x3cc4bd6d,0xbd800000,0x3cc43d6d,0x3d35bd35,0xbd6dbcc4,0x3d80,0x3d6dbcc4,0xbd35bd35,0xbcc43d6d,0x3d800000,0xbcc4bd6d,0xbd353d35,0x3d6d3cc4,
0xbd80,0xbd6d3cc4,0x3d353d35,0x3cc4bd6d,0xbd800000,0x3cc43d6d,0x3d35bd35,0xbd6dbcc4,0x3d80,0x3d6dbcc4,0xbd35bd35,0xbcc43d6d,0x3d800000,0xbcc4bd6d,0xbd353d35,0x3d6d3cc4,
0xbd353d35,0x3d553d0e,0x3cc4bd6d,0xbd7bbc48,0xbd800000,0x3c483d7b,0x3d6dbcc4,0xbd0ebd55,0xbd35bd35,0xbd0e3d55,0x3d6d3cc4,0x3c48bd7b,0xbd80,0xbd7b3c48,0x3cc43d6d,0x3d55bd0e,
0x3d35bd35,0xbd55bd0e,0xbcc43d6d,0x3d7b3c48,0x3d800000,0xbc48bd7b,0xbd6d3cc4,0x3d0e3d55,0x3d353d35,0x3d0ebd55,0xbd6dbcc4,0xbc483d7b,0x3d80,0x3d7bbc48,0xbcc4bd6d,0xbd553d0e,
0xbd800000,0x3d800000,0xbd800000,0x3d800000,0xbd800000,0x3d800000,0xbd800000,0x3d800000,0xbd800000,0x3d800000,0xbd800000,0x3d800000,0xbd800000,0x3d800000,0xbd800000,0x3d800000,
0xbd800000,0x3d800000,0xbd800000,0x3d800000,0xbd800000,0x3d800000,0xbd800000,0x3d800000,0xbd800000,0x3d800000,0xbd800000,0x3d800000,0xbd800000,0x3d800000,0xbd800000,0x3d800000,
0xbd35bd35,0x3d0e3d55,0xbcc4bd6d,0x3c483d7b,0xbd800000,0x3d7b3c48,0xbd6dbcc4,0x3d553d0e,0x3d35bd35,0xbd553d0e,0x3d6dbcc4,0xbd7b3c48,0x8000bd80,0xbc483d7b,0x3cc4bd6d,0xbd0e3d55,
0x3d353d35,0xbd0ebd55,0x3cc43d6d,0xbc48bd7b,0x3d800000,0xbd7bbc48,0x3d6d3cc4,0xbd55bd0e,0xbd353d35,0x3d55bd0e,0xbd6d3cc4,0x3d7bbc48,0x80003d80,0x3c48bd7b,0xbcc43d6d,0x3d0ebd55,
0x3d800000,0xbd6dbcc4,0x3d353d35,0xbcc4bd6d,0x80003d80,0x3cc4bd6d,0xbd353d35,0x3d6dbcc4,0xbd800000,0x3d6d3cc4,0xbd35bd35,0x3cc43d6d,0x8000bd80,0xbcc43d6d,0x3d35bd35,0xbd6d3cc4,
0x3d800000,0xbd6dbcc4,0x3d353d35,0xbcc4bd6d,0x80003d80,0x3cc4bd6d,0xbd353d35,0x3d6dbcc4,0xbd800000,0x3d6d3cc4,0xbd35bd35,0x3cc43d6d,0x8000bd80,0xbcc43d6d,0x3d35bd35,0xbd6d3cc4,
0xbd35bd35,0x3c483d7b,0x3cc4bd6d,0xbd553d0e,0x80003d80,0x3d0ebd55,0xbd6d3cc4,0x3d7b3c48,0x3d35bd35,0xbd7b3c48,0x3d6d3cc4,0xbd0ebd55,0xbd800000,0x3d553d0e,0xbcc4bd6d,0xbc483d7b,
0x3d353d35,0xbc48bd7b,0xbcc43d6d,0x3d55bd0e,0x8000bd80,0xbd0e3d55,0x3d6dbcc4,0xbd7bbc48,0xbd353d35,0x3d7bbc48,0xbd6dbcc4,0x3d0e3d55,0x3d800000,0xbd55bd0e,0x3cc43d6d,0x3c48bd7b,
0xbd800000,0x3d353d35,0x8000bd80,0xbd353d35,0x3d800000,0xbd35bd35,0x80003d80,0x3d35bd35,0xbd800000,0x3d353d35,0x8000bd80,0xbd353d35,0x3d800000,0xbd35bd35,0x80003d80,0x3d35bd35,
0xbd800000,0x3d353d35,0x8000bd80,0xbd353d35,0x3d800000,0xbd35bd35,0x80003d80,0x3d35bd35,0xbd800000,0x3d353d35,0x8000bd80,0xbd353d35,0x3d800000,0xbd35bd35,0x80003d80,0x3d35bd35,
0xbd35bd35,0xbc483d7b,0x3d6dbcc4,0xbd55bd0e,0x3d800000,0xbd0ebd55,0xbcc43d6d,0x3d7bbc48,0x3d35bd35,0xbd7bbc48,0x3cc43d6d,0x3d0ebd55,0x80003d80,0x3d55bd0e,0xbd6dbcc4,0x3c483d7b,
0x3d353d35,0x3c48bd7b,0xbd6d3cc4,0x3d553d0e,0xbd800000,0x3d0e3d55,0x3cc4bd6d,0xbd7b3c48,0xbd353d35,0x3d7b3c48,0xbcc4bd6d,0xbd0e3d55,0x8000bd80,0xbd553d0e,0x3d6d3cc4,0xbc48bd7b,
0x3d800000,0xbcc4bd6d,0xbd353d35,0x3d6d3cc4,0x8000bd80,0xbd6d3cc4,0x3d353d35,0x3cc4bd6d,0xbd800000,0x3cc43d6d,0x3d35bd35,0xbd6dbcc4,0x80003d80,0x3d6dbcc4,0xbd35bd35,0xbcc43d6d,
0x3d800000,0xbcc4bd6d,0xbd353d35,0x3d6d3cc4,0x8000bd80,0xbd6d3cc4,0x3d353d35,0x3cc4bd6d,0xbd800000,0x3cc43d6d,0x3d35bd35,0xbd6dbcc4,0x80003d80,0x3d6dbcc4,0xbd35bd35,0xbcc43d6d,
0xbd35bd35,0xbd0e3d55,0x3d6d3cc4,0x3c48bd7b,0x8000bd80,0xbd7b3c48,0x3cc43d6d,0x3d55bd0e,0x3d35bd35,0xbd55bd0e,0xbcc43d6d,0x3d7b3c48,0x3d800000,0xbc48bd7b,0xbd6d3cc4,0x3d0e3d55,
0x3d353d35,0x3d0ebd55,0xbd6dbcc4,0xbc483d7b,0x80003d80,0x3d7bbc48,0xbcc4bd6d,0xbd553d0e,0xbd353d35,0x3d553d0e,0x3cc4bd6d,0xbd7bbc48,0xbd800000,0x3c483d7b,0x3d6dbcc4,0xbd0ebd55,
0x3d80,0x3d800000,0xbd80,0xbd800000,0x3d80,0x3d800000,0xbd80,0xbd800000,0x3d80,0x3d800000,0xbd80,0xbd800000,0x3d80,0x3d800000,0xbd80,0xbd800000,
0x3d80,0x3d800000,0xbd80,0xbd800000,0x3d80,0x3d800000,0xbd80,0xbd800000,0x3d80,0x3d800000,0xbd80,0xbd800000,0x3d80,0x3d800000,0xbd80,0xbd800000,
0xbd353d35,0x3d0e3d55,0x3d6dbcc4,0xbc48bd7b,0x3d80,0x3d7b3c48,0x3cc4bd6d,0xbd55bd0e,0xbd35bd35,0xbd553d0e,0x3cc43d6d,0x3d7bbc48,0xbd800000,0xbc483d7b,0x3d6d3cc4,0x3d0ebd55,
0x3d35bd35,0xbd0ebd55,0xbd6d3cc4,0x3c483d7b,0xbd80,0xbd7bbc48,0xbcc43d6d,0x3d553d0e,0x3d353d35,0x3d55bd0e,0xbcc4bd6d,0xbd7b3c48,0x3d800000,0x3c48bd7b,0xbd6dbcc4,0xbd0e3d55,
0xbd80,0xbd6dbcc4,0xbd353d35,0x3cc43d6d,0x3d800000,0x3cc4bd6d,0xbd35bd35,0xbd6d3cc4,0x3d80,0x3d6d3cc4,0x3d35bd35,0xbcc4bd6d,0xbd800000,0xbcc43d6d,0x3d353d35,0x3d6dbcc4,
0xbd80,0xbd6dbcc4,0xbd353d35,0x3cc43d6d,0x3d800000,0x3cc4bd6d,0xbd35bd35,0xbd6d3cc4,0x3d80,0x3d6d3cc4,0x3d35bd35,0xbcc4bd6d,0xbd800000,0xbcc43d6d,0x3d353d35,0x3d6dbcc4,
0xbd353d35,0x3c483d7b,0x3d6d3cc4,0x3d55bd0e,0x3d800000,0x3d0ebd55,0xbcc4bd6d,0xbd7bbc48,0xbd35bd35,0xbd7b3c48,0xbcc43d6d,0x3d0e3d55,0x3d80,0x3d553d0e,0x3d6dbcc4,0x3c48bd7b,
0x3d35bd35,0xbc48bd7b,0xbd6dbcc4,0xbd553d0e,0xbd800000,0xbd0e3d55,0x3cc43d6d,0x3d7b3c48,0x3d353d35,0x3d7bbc48,0x3cc4bd6d,0xbd0ebd55,0xbd80,0xbd55bd0e,0xbd6d3cc4,0xbc483d7b,
0x3d80,0x3d353d35,0x3d800000,0x3d35bd35,0xbd80,0xbd35bd35,0xbd800000,0xbd353d35,0x3d80,0x3d353d35,0x3d800000,0x3d35bd35,0xbd80,0xbd35bd35,0xbd800000,0xbd353d35,
0x3d80,0x3d353d35,0x3d800000,0x3d35bd35,0xbd80,0xbd35bd35,0xbd800000,0xbd353d35,0x3d80,0x3d353d35,0x3d800000,0x3d35bd35,0xbd80,0xbd35bd35,0xbd800000,0xbd353d35,
0xbd353d35,0xbc483d7b,0x3cc43d6d,0x3d553d0e,0xbd80,0xbd0ebd55,0xbd6dbcc4,0xbd7b3c48,0xbd35bd35,0xbd7bbc48,0xbd6d3cc4,0xbd0e3d55,0x3d800000,0x3d55bd0e,0x3cc4bd6d,0xbc48bd7b,
0x3d35bd35,0x3c48bd7b,0xbcc4bd6d,0xbd55bd0e,0x3d80,0x3d0e3d55,0x3d6d3cc4,0x3d7bbc48,0x3d353d35,0x3d7b3c48,0x3d6dbcc4,0x3d0ebd55,0xbd800000,0xbd553d0e,0xbcc43d6d,0x3c483d7b,
0xbd80,0xbcc4bd6d,0xbd35bd35,0xbd6dbcc4,0xbd800000,0xbd6d3cc4,0xbd353d35,0xbcc43d6d,0x3d80,0x3cc43d6d,0x3d353d35,0x3d6d3cc4,0x3d800000,0x3d6dbcc4,0x3d35bd35,0x3cc4bd6d,
0xbd80,0xbcc4bd6d,0xbd35bd35,0xbd6dbcc4,0xbd800000,0xbd6d3cc4,0xbd353d35,0xbcc43d6d,0x3d80,0x3cc43d6d,0x3d353d35,0x3d6d3cc4,0x3d800000,0x3d6dbcc4,0x3d35bd35,0x3cc4bd6d,
0xbd353d35,0xbd0e3d55,0xbcc43d6d,0xbc483d7b,0xbd800000,0xbd7b3c48,0xbd6d3cc4,0xbd553d0e,0xbd35bd35,0xbd55bd0e,0xbd6dbcc4,0xbd7bbc48,0xbd80,0xbc48bd7b,0xbcc4bd6d,0xbd0ebd55,
0x3d35bd35,0x3d0ebd55,0x3cc4bd6d,0x3c48bd7b,0x3d800000,0x3d7bbc48,0x3d6dbcc4,0x3d55bd0e,0x3d353d35,0x3d553d0e,0x3d6d3cc4,0x3d7b3c48,0x3d80,0x3c483d7b,0x3cc43d6d,0x3d0e3d55,
0xbd800000,0x80003d80,0x3d800000,0x8000bd80,0xbd800000,0x80003d80,0x3d800000,0x8000bd80,0xbd800000,0x80003d80,0x3d800000,0x8000bd80,0xbd800000,0x80003d80,0x3d800000,0x8000bd80,
0xbd800000,0x80003d80,0x3d800000,0x8000bd80,0xbd800000,0x80003d80,0x3d800000,0x8000bd80,0xbd800000,0x80003d80,0x3d800000,0x8000bd80,0xbd800000,0x80003d80,0x3d800000,0x8000bd80,
0xbd35bd35,0xbd553d0e,0x3cc43d6d,0x3d7bbc48,0xbd800000,0xbc483d7b,0x3d6d3cc4,0x3d0ebd55,0x3d35bd35,0xbd0ebd55,0xbd6d3cc4,0x3c483d7b,0x8000bd80,0xbd7bbc48,0xbcc43d6d,0x3d553d0e,
0x3d353d35,0x3d55bd0e,0xbcc4bd6d,0xbd7b3c48,0x3d800000,0x3c48bd7b,0xbd6dbcc4,0xbd0e3d55,0xbd353d35,0x3d0e3d55,0x3d6dbcc4,0xbc48bd7b,0x80003d80,0x3d7b3c48,0x3cc4bd6d,0xbd55bd0e,
0x3d800000,0x3cc4bd6d,0xbd35bd35,0xbd6d3cc4,0x80003d80,0x3d6d3cc4,0x3d35bd35,0xbcc4bd6d,0xbd800000,0xbcc43d6d,0x3d353d35,0x3d6dbcc4,0x8000bd80,0xbd6dbcc4,0xbd353d35,0x3cc43d6d,
0x3d800000,0x3cc4bd6d,0xbd35bd35,0xbd6d3cc4,0x80003d80,0x3d6d3cc4,0x3d35bd35,0xbcc4bd6d,0xbd800000,0xbcc43d6d,0x3d353d35,0x3d6dbcc4,0x8000bd80,0xbd6dbcc4,0xbd353d35,0x3cc43d6d,
0xbd35bd35,0xbd7b3c48,0xbcc43d6d,0x3d0e3d55,0x80003d80,0x3d553d0e,0x3d6dbcc4,0x3c48bd7b,0x3d35bd35,0xbc48bd7b,0xbd6dbcc4,0xbd553d0e,0xbd800000,0xbd0e3d55,0x3cc43d6d,0x3d7b3c48,
0x3d353d35,0x3d7bbc48,0x3cc4bd6d,0xbd0ebd55,0x8000bd80,0xbd55bd0e,0xbd6d3cc4,0xbc483d7b,0xbd353d35,0x3c483d7b,0x3d6d3cc4,0x3d55bd0e,0x3d800000,0x3d0ebd55,0xbcc4bd6d,0xbd7bbc48,
0xbd800000,0xbd353d35,0x80003d80,0x3d353d35,0x3d800000,0x3d35bd35,0x8000bd80,0xbd35bd35,0xbd800000,0xbd353d35,0x80003d80,0x3d353d35,0x3d800000,0x3d35bd35,0x8000bd80,0xbd35bd35,
0xbd800000,0xbd353d35,0x80003d80,0x3d353d35,0x3d800000,0x3d35bd35,0x8000bd80,0xbd35bd35,0xbd800000,0xbd353d35,0x80003d80,0x3d353d35,0x3d800000,0x3d35bd35,0x8000bd80,0xbd35bd35,
0xbd35bd35,0xbd7bbc48,0xbd6d3cc4,0xbd0e3d55,0x3d800000,0x3d55bd0e,0x3cc4bd6d,0xbc48bd7b,0x3d35bd35,0x3c48bd7b,0xbcc4bd6d,0xbd55bd0e,0x80003d80,0x3d0e3d55,0x3d6d3cc4,0x3d7bbc48,
0x3d353d35,0x3d7b3c48,0x3d6dbcc4,0x3d0ebd55,0xbd800000,0xbd553d0e,0xbcc43d6d,0x3c483d7b,0xbd353d35,0xbc483d7b,0x3cc43d6d,0x3d553d0e,0x8000bd80,0xbd0ebd55,0xbd6dbcc4,0xbd7b3c48,
0x3d800000,0x3d6dbcc4,0x3d35bd35,0x3cc4bd6d,0x8000bd80,0xbcc4bd6d,0xbd35bd35,0xbd6dbcc4,0xbd800000,0xbd6d3cc4,0xbd353d35,0xbcc43d6d,0x80003d80,0x3cc43d6d,0x3d353d35,0x3d6d3cc4,
0x3d800000,0x3d6dbcc4,0x3d35bd35,0x3cc4bd6d,0x8000bd80,0xbcc4bd6d,0xbd35bd35,0xbd6dbcc4,0xbd800000,0xbd6d3cc4,0xbd353d35,0xbcc43d6d,0x80003d80,0x3cc43d6d,0x3d353d35,0x3d6d3cc4,
0xbd35bd35,0xbd55bd0e,0xbd6dbcc4,0xbd7bbc48,0x8000bd80,0xbc48bd7b,0xbcc4bd6d,0xbd0ebd55,0x3d35bd35,0x3d0ebd55,0x3cc4bd6d,0x3c48bd7b,0x3d800000,0x3d7bbc48,0x3d6dbcc4,0x3d55bd0e,
0x3d353d35,0x3d553d0e,0x3d6d3cc4,0x3d7b3c48,0x80003d80,0x3c483d7b,0x3cc43d6d,0x3d0e3d55,0xbd353d35,0xbd0e3d55,0xbcc43d6d,0xbc483d7b,0xbd800000,0xbd7b3c48,0xbd6d3cc4,0xbd553d0e,
0x3d80,0xbb493d80,0xbbc93d7f,0xbc163d7d,0xbc483d7b,0xbc793d78,0xbc953d75,0xbcac3d71,0xbcc43d6d,0xbcdb3d67,0xbcf13d62,0xbd043d5c,0xbd0e3d55,0xbd183d4e,0xbd223d46,0xbd2c3d3e,
0xbd353d35,0xbd3e3d2c,0xbd463d22,0xbd4e3d18,0xbd553d0e,0xbd5c3d04,0xbd623cf1,0xbd673cdb,0xbd6d3cc4,0xbd713cac,0xbd753c95,0xbd783c79,0xbd7b3c48,0xbd7d3c16,0xbd7f3bc9,0xbd803b49,
0xbd553d0e,0xbd713cac,0xbd7f3bc9,0xbd7dbc16,0x3d80,0xbc793d78,0xbcf13d62,0xbd2c3d3e,0xbc48bd7b,0x3b49bd80,0x3c95bd75,0x3d04bd5c,0xbd6dbcc4,0xbd4ebd18,0xbd22bd46,0xbcdbbd67,
0x3d7b3c48,0x3d673cdb,0x3d463d22,0x3d183d4e,0x3d35bd35,0x3d5cbd04,0x3d75bc95,0x3d80bb49,0xbd0e3d55,0xbd3e3d2c,0xbd623cf1,0xbd783c79,0x3cc43d6d,0x3c163d7d,0xbbc93d7f,0xbcac3d71,
0x3cc4bd6d,0x3d3ebd2c,0x3d75bc95,0x3d7d3c16,0x3d553d0e,0x3d043d5c,0x3bc93d7f,0xbcac3d71,0x3d80,0xbcdb3d67,0xbd463d22,0xbd783c79,0xbd7bbc48,0xbd4ebd18,0xbcf1bd62,0xbb49bd80,
0x3d6dbcc4,0x3d803b49,0x3d623cf1,0x3d183d4e,0x3c483d7b,0xbc793d78,0xbd223d46,0xbd673cdb,0xbd353d35,0xbd713cac,0xbd7fbbc9,0xbd5cbd04,0xbd0ebd55,0xbc16bd7d,0x3c95bd75,0x3d2cbd3e,
0xbd7b3c48,0xbd67bcdb,0xbcf1bd62,0x3c16bd7d,0x3d6d3cc4,0x3d043d5c,0xbbc93d7f,0xbd2c3d3e,0xbd0ebd55,0x3b49bd80,0x3d22bd46,0x3d78bc79,0x3d80,0xbd183d4e,0xbd753c95,0xbd71bcac,
0x3d553d0e,0x3cac3d71,0xbc953d75,0xbd4e3d18,0xbcc4bd6d,0x3c79bd78,0x3d46bd22,0x3d80bb49,0xbc483d7b,0xbd3e3d2c,0xbd7f3bc9,0xbd5cbd04,0x3d35bd35,0x3d7dbc16,0x3d623cf1,0x3cdb3d67,
0xbd353d35,0xbd80bb49,0xbd22bd46,0x3c16bd7d,0x3d55bd0e,0x3d783c79,0x3cf13d62,0xbcac3d71,0xbd6d3cc4,0xbd67bcdb,0xbc95bd75,0x3d04bd5c,0x3d7bbc48,0x3d4e3d18,0x3bc93d7f,0xbd2c3d3e,
0x3d80,0xbd3e3d2c,0xbd7fbbc9,0xbd18bd4e,0x3c48bd7b,0x3d5cbd04,0x3d753c95,0x3cdb3d67,0xbcc43d6d,0xbd713cac,0xbd62bcf1,0xbc79bd78,0x3d0ebd55,0x3d7dbc16,0x3d463d22,0x3b493d80,
0xbd7bbc48,0xbcacbd71,0x3d22bd46,0x3d7d3c16,0x3d35bd35,0x3d783c79,0x3c953d75,0xbd2c3d3e,0x3d0ebd55,0x3d803b49,0x3cf13d62,0xbd043d5c,0x3cc43d6d,0xbd183d4e,0xbd7fbbc9,0xbcdbbd67,
0x3d55bd0e,0x3d673cdb,0x3bc93d7f,0xbd4e3d18,0x3d80,0xbd5c3d04,0xbd62bcf1,0xbb49bd80,0x3c483d7b,0xbd3e3d2c,0xbd75bc95,0xbc79bd78,0xbd6dbcc4,0xbc16bd7d,0x3d46bd22,0x3d713cac,
0x3d6dbcc4,0x3d2c3d3e,0xbcf13d62,0xbd7dbc16,0xbc48bd7b,0x3d5cbd04,0x3d463d22,0xbcac3d71,0xbd353d35,0xbd67bcdb,0x3bc9bd7f,0x3d78bc79,0x3d0e3d55,0xbd183d4e,0xbd75bc95,0xbb49bd80,
0x3cc4bd6d,0x3d803b49,0x3c953d75,0xbd4e3d18,0xbd55bd0e,0x3c79bd78,0x3d7fbbc9,0x3cdb3d67,0x3d80,0xbd713cac,0xbd22bd46,0x3d04bd5c,0x3d7b3c48,0x3c163d7d,0xbd623cf1,0xbd3ebd2c,
0xbd55bd0e,0x3cdbbd67,0x3d753c95,0xbc163d7d,0xbcc4bd6d,0x3d5cbd04,0x3d223d46,0xbd2c3d3e,0x3c48bd7b,0x3d803b49,0x3bc93d7f,0xbd783c79,0x3d35bd35,0x3d4e3d18,0xbcf13d62,0xbd71bcac,
0x3d7bbc48,0x3cac3d71,0xbd623cf1,0xbd18bd4e,0x3d6d3cc4,0xbc793d78,0xbd7fbbc9,0xbb49bd80,0x3d0e3d55,0xbd3e3d2c,0xbd46bd22,0x3d04bd5c,0x3d80,0xbd7d3c16,0xbc95bd75,0x3d67bcdb,
0xbd800000,0xbd80bb49,0xbd7fbbc9,0xbd7dbc16,0xbd7bbc48,0xbd78bc79,0xbd75bc95,0xbd71bcac,0xbd6dbcc4,0xbd67bcdb,0xbd62bcf1,0xbd5cbd04,0xbd55bd0e,0xbd4ebd18,0xbd46bd22,0xbd3ebd2c,
0xbd35bd35,0xbd2cbd3e,0xbd22bd46,0xbd18bd4e,0xbd0ebd55,0xbd04bd5c,0xbcf1bd62,0xbcdbbd67,0xbcc4bd6d,0xbcacbd71,0xbc95bd75,0xbc79bd78,0xbc48bd7b,0xbc16bd7d,0xbbc9bd7f,0xbb49bd80,
0xbd0ebd55,0xbcacbd71,0xbbc9bd7f,0x3c16bd7d,0xbd800000,0xbd78bc79,0xbd62bcf1,0xbd3ebd2c,0x3d7bbc48,0x3d803b49,0x3d753c95,0x3d5c3d04,0x3cc4bd6d,0x3d18bd4e,0x3d46bd22,0x3d67bcdb,
0xbc483d7b,0xbcdb3d67,0xbd223d46,0xbd4e3d18,0x3d353d35,0x3d043d5c,0x3c953d75,0x3b493d80,0xbd55bd0e,0xbd2cbd3e,0xbcf1bd62,0xbc79bd78,0xbd6d3cc4,0xbd7d3c16,0xbd7fbbc9,0xbd71bcac,
0x3d6d3cc4,0x3d2c3d3e,0x3c953d75,0xbc163d7d,0xbd0e3d55,0xbd5c3d04,0xbd7f3bc9,0xbd71bcac,0xbd800000,0xbd67bcdb,0xbd22bd46,0xbc79bd78,0x3c48bd7b,0x3d18bd4e,0x3d62bcf1,0x3d80bb49,
0x3cc43d6d,0xbb493d80,0xbcf13d62,0xbd4e3d18,0xbd7b3c48,0xbd78bc79,0xbd46bd22,0xbcdbbd67,0xbd35bd35,0xbcacbd71,0x3bc9bd7f,0x3d04bd5c,0x3d55bd0e,0x3d7dbc16,0x3d753c95,0x3d3e3d2c,
0xbc48bd7b,0x3cdbbd67,0x3d62bcf1,0x3d7d3c16,0xbcc43d6d,0xbd5c3d04,0xbd7fbbc9,0xbd3ebd2c,0x3d55bd0e,0x3d803b49,0x3d463d22,0x3c793d78,0xbd800000,0xbd4ebd18,0xbc95bd75,0x3cacbd71,
0xbd0e3d55,0xbd713cac,0xbd75bc95,0xbd18bd4e,0x3d6dbcc4,0x3d783c79,0x3d223d46,0x3b493d80,0xbd7bbc48,0xbd2cbd3e,0xbbc9bd7f,0x3d04bd5c,0x3d353d35,0x3c163d7d,0xbcf13d62,0xbd673cdb,
0xbd35bd35,0x3b49bd80,0x3d46bd22,0x3d7d3c16,0x3d0e3d55,0xbc793d78,0xbd623cf1,0xbd71bcac,0xbcc4bd6d,0x3cdbbd67,0x3d75bc95,0x3d5c3d04,0x3c483d7b,0xbd183d4e,0xbd7f3bc9,0xbd3ebd2c,
0xbd800000,0xbd2cbd3e,0x3bc9bd7f,0x3d4ebd18,0x3d7b3c48,0x3d043d5c,0xbc953d75,0xbd673cdb,0xbd6dbcc4,0xbcacbd71,0x3cf1bd62,0x3d78bc79,0x3d553d0e,0x3c163d7d,0xbd223d46,0xbd803b49,
0x3c48bd7b,0x3d71bcac,0x3d463d22,0xbc163d7d,0x3d353d35,0xbc793d78,0xbd753c95,0xbd3ebd2c,0x3d553d0e,0xbb493d80,0xbd623cf1,0xbd5cbd04,0xbd6d3cc4,0xbd4ebd18,0x3bc9bd7f,0x3d67bcdb,
0x3d0e3d55,0xbcdb3d67,0xbd7f3bc9,0xbd18bd4e,0xbd800000,0xbd04bd5c,0x3cf1bd62,0x3d80bb49,0xbd7b3c48,0xbd2cbd3e,0x3c95bd75,0x3d78bc79,0x3cc4bd6d,0x3d7dbc16,0x3d223d46,0xbcac3d71,
0x3cc43d6d,0xbd3e3d2c,0xbd62bcf1,0x3c16bd7d,0x3d7bbc48,0x3d043d5c,0xbd223d46,0xbd71bcac,0xbd35bd35,0x3cdbbd67,0x3d7f3bc9,0x3c793d78,0xbd553d0e,0xbd4ebd18,0x3c95bd75,0x3d80bb49,
0x3d6d3cc4,0xbb493d80,0xbd753c95,0xbd18bd4e,0x3d0ebd55,0x3d783c79,0x3bc93d7f,0xbd673cdb,0xbd800000,0xbcacbd71,0x3d46bd22,0x3d5c3d04,0xbc483d7b,0xbd7d3c16,0xbcf1bd62,0x3d2cbd3e,
0x3d0ebd55,0x3d673cdb,0xbc953d75,0xbd7dbc16,0x3d6dbcc4,0x3d043d5c,0xbd463d22,0xbd3ebd2c,0x3d7b3c48,0xbb493d80,0xbd7f3bc9,0xbc79bd78,0x3d353d35,0xbd183d4e,0xbd62bcf1,0x3cacbd71,
0x3c483d7b,0xbd713cac,0xbcf1bd62,0x3d4ebd18,0xbcc43d6d,0xbd78bc79,0x3bc9bd7f,0x3d80bb49,0xbd553d0e,0xbd2cbd3e,0x3d22bd46,0x3d5c3d04,0xbd800000,0xbc16bd7d,0x3d75bc95,0x3cdb3d67,
0x3d80,0xbd80bb49,0x3bc9bd7f,0x3d7d3c16,0xbc483d7b,0xbd78bc79,0x3c95bd75,0x3d713cac,0xbcc43d6d,0xbd67bcdb,0x3cf1bd62,0x3d5c3d04,0xbd0e3d55,0xbd4ebd18,0x3d22bd46,0x3d3e3d2c,
0xbd353d35,0xbd2cbd3e,0x3d46bd22,0x3d183d4e,0xbd553d0e,0xbd04bd5c,0x3d62bcf1,0x3cdb3d67,0xbd6d3cc4,0xbcacbd71,0x3d75bc95,0x3c793d78,0xbd7b3c48,0xbc16bd7d,0x3d7fbbc9,0x3b493d80,
0xbd553d0e,0xbcacbd71,0x3d7fbbc9,0xbc163d7d,0x3d80,0xbd78bc79,0x3cf1bd62,0x3d3e3d2c,0xbc48bd7b,0x3d803b49,0xbc953d75,0xbd5cbd04,0xbd6dbcc4,0x3d18bd4e,0x3d223d46,0xbd673cdb,
0x3d7b3c48,0xbcdb3d67,0xbd46bd22,0x3d4ebd18,0x3d35bd35,0x3d043d5c,0xbd753c95,0xbb49bd80,0xbd0e3d55,0xbd2cbd3e,0x3d62bcf1,0x3c793d78,0x3cc43d6d,0xbd7d3c16,0x3bc9bd7f,0x3d713cac,
0x3cc4bd6d,0x3d2c3d3e,0xbd753c95,0x3c16bd7d,0x3d553d0e,0xbd5c3d04,0xbbc9bd7f,0x3d713cac,0x3d80,0xbd67bcdb,0x3d46bd22,0x3c793d78,0xbd7bbc48,0x3d18bd4e,0x3cf13d62,0xbd803b49,
0x3d6dbcc4,0xbb493d80,0xbd62bcf1,0x3d4ebd18,0x3c483d7b,0xbd78bc79,0x3d22bd46,0x3cdb3d67,0xbd353d35,0xbcacbd71,0x3d7f3bc9,0xbd043d5c,0xbd0ebd55,0x3d7dbc16,0xbc953d75,0xbd3ebd2c,
0xbd7b3c48,0x3cdbbd67,0x3cf13d62,0xbd7dbc16,0x3d6d3cc4,0xbd5c3d04,0x3bc9bd7f,0x3d3e3d2c,0xbd0ebd55,0x3d803b49,0xbd223d46,0xbc79bd78,0x3d80,0xbd4ebd18,0x3d75bc95,0xbcac3d71,
0x3d553d0e,0xbd713cac,0x3c95bd75,0x3d183d4e,0xbcc4bd6d,0x3d783c79,0xbd463d22,0xbb49bd80,0xbc483d7b,0xbd2cbd3e,0x3d7fbbc9,0xbd043d5c,0x3d35bd35,0x3c163d7d,0xbd62bcf1,0x3d67bcdb,
0xbd353d35,0x3b49bd80,0x3d223d46,0xbd7dbc16,0x3d55bd0e,0xbc793d78,0xbcf1bd62,0x3d713cac,0xbd6d3cc4,0x3cdbbd67,0x3c953d75,0xbd5cbd04,0x3d7bbc48,0xbd183d4e,0xbbc9bd7f,0x3d3e3d2c,
0x3d80,0xbd2cbd3e,0x3d7f3bc9,0xbd4e3d18,0x3c48bd7b,0x3d043d5c,0xbd75bc95,0x3d67bcdb,0xbcc43d6d,0xbcacbd71,0x3d623cf1,0xbd783c79,0x3d0ebd55,0x3c163d7d,0xbd46bd22,0x3d80bb49,
0xbd7bbc48,0x3d71bcac,0xbd223d46,0x3c16bd7d,0x3d35bd35,0xbc793d78,0xbc95bd75,0x3d3e3d2c,0x3d0ebd55,0xbb493d80,0xbcf1bd62,0x3d5c3d04,0x3cc43d6d,0xbd4ebd18,0x3d7f3bc9,0xbd673cdb,
0x3d55bd0e,0xbcdb3d67,0xbbc9bd7f,0x3d183d4e,0x3d80,0xbd04bd5c,0x3d623cf1,0xbd803b49,0x3c483d7b,0xbd2cbd3e,0x3d753c95,0xbd783c79,0xbd6dbcc4,0x3d7dbc16,0xbd463d22,0x3cacbd71,
0x3d6dbcc4,0xbd3e3d2c,0x3cf1bd62,0xbc163d7d,0xbc48bd7b,0x3d043d5c,0xbd46bd22,0x3d713cac,0xbd353d35,0x3cdbbd67,0xbbc93d7f,0xbc79bd78,0x3d0e3d55,0xbd4ebd18,0x3d753c95,0xbd803b49,
0x3cc4bd6d,0xbb493d80,0xbc95bd75,0x3d183d4e,0xbd55bd0e,0x3d783c79,0xbd7f3bc9,0x3d67bcdb,0x3d80,0xbcacbd71,0x3d223d46,0xbd5cbd04,0x3d7b3c48,0xbd7d3c16,0x3d62bcf1,0xbd2c3d3e,
0xbd55bd0e,0x3d673cdb,0xbd75bc95,0x3d7d3c16,0xbcc4bd6d,0x3d043d5c,0xbd22bd46,0x3d3e3d2c,0x3c48bd7b,0xbb493d80,0xbbc9bd7f,0x3c793d78,0x3d35bd35,0xbd183d4e,0x3cf1bd62,0xbcac3d71,
0x3d7bbc48,0xbd713cac,0x3d62bcf1,0xbd4e3d18,0x3d6d3cc4,0xbd78bc79,0x3d7f3bc9,0xbd803b49,0x3d0e3d55,0xbd2cbd3e,0x3d463d22,0xbd5cbd04,0x3d80,0xbc16bd7d,0x3c953d75,0xbcdbbd67,
0xbd800000,0x3b49bd80,0x3d7f3bc9,0xbc163d7d,0xbd7bbc48,0x3c79bd78,0x3d753c95,0xbcac3d71,0xbd6dbcc4,0x3cdbbd67,0x3d623cf1,0xbd043d5c,0xbd55bd0e,0x3d18bd4e,0x3d463d22,0xbd2c3d3e,
0xbd35bd35,0x3d3ebd2c,0x3d223d46,0xbd4e3d18,0xbd0ebd55,0x3d5cbd04,0x3cf13d62,0xbd673cdb,0xbcc4bd6d,0x3d71bcac,0x3c953d75,0xbd783c79,0xbc48bd7b,0x3d7dbc16,0x3bc93d7f,0xbd803b49,
0xbd0ebd55,0x3d71bcac,0x3bc93d7f,0xbd7dbc16,0xbd800000,0x3c79bd78,0x3d623cf1,0xbd2c3d3e,0x3d7bbc48,0xbb493d80,0xbd75bc95,0x3d04bd5c,0x3cc4bd6d,0x3d4e3d18,0xbd463d22,0xbcdbbd67,
0xbc483d7b,0xbd67bcdb,0x3d22bd46,0x3d183d4e,0x3d353d35,0xbd5c3d04,0xbc95bd75,0x3d80bb49,0xbd55bd0e,0x3d3ebd2c,0x3cf13d62,0xbd783c79,0xbd6d3cc4,0xbc16bd7d,0x3d7f3bc9,0xbcac3d71,
0x3d6d3cc4,0xbd3e3d2c,0xbc95bd75,0x3d7d3c16,0xbd0e3d55,0xbd04bd5c,0x3d7fbbc9,0xbcac3d71,0xbd800000,0x3cdbbd67,0x3d223d46,0xbd783c79,0x3c48bd7b,0x3d4e3d18,0xbd623cf1,0xbb49bd80,
0x3cc43d6d,0xbd80bb49,0x3cf1bd62,0x3d183d4e,0xbd7b3c48,0x3c79bd78,0x3d463d22,0xbd673cdb,0xbd35bd35,0x3d71bcac,0xbbc93d7f,0xbd5cbd04,0x3d55bd0e,0x3c163d7d,0xbd75bc95,0x3d2cbd3e,
0xbc48bd7b,0x3d673cdb,0xbd623cf1,0x3c16bd7d,0xbcc43d6d,0xbd04bd5c,0x3d7f3bc9,0xbd2c3d3e,0x3d55bd0e,0xbb493d80,0xbd46bd22,0x3d78bc79,0xbd800000,0x3d18bd4e,0x3c953d75,0xbd71bcac,
0xbd0e3d55,0xbcacbd71,0x3d753c95,0xbd4e3d18,0x3d6dbcc4,0xbc793d78,0xbd22bd46,0x3d80bb49,0xbd7bbc48,0x3d3ebd2c,0x3bc93d7f,0xbd5cbd04,0x3d353d35,0xbd7d3c16,0x3cf1bd62,0x3cdb3d67,
0xbd35bd35,0x3d803b49,0xbd463d22,0x3c16bd7d,0x3d0e3d55,0xbd78bc79,0x3d62bcf1,0xbcac3d71,0xbcc4bd6d,0x3d673cdb,0xbd753c95,0x3d04bd5c,0x3c483d7b,0xbd4ebd18,0x3d7fbbc9,0xbd2c3d3e,
0xbd800000,0x3d3ebd2c,0xbbc93d7f,0xbd18bd4e,0x3d7b3c48,0xbd5c3d04,0x3c95bd75,0x3cdb3d67,0xbd6dbcc4,0x3d71bcac,0xbcf13d62,0xbc79bd78,0x3d553d0e,0xbd7d3c16,0x3d22bd46,0x3b493d80,
0x3c48bd7b,0x3cac3d71,0xbd46bd22,0x3d7d3c16,0x3d353d35,0xbd78bc79,0x3d75bc95,0xbd2c3d3e,0x3d553d0e,0xbd80bb49,0x3d62bcf1,0xbd043d5c,0xbd6d3cc4,0x3d18bd4e,0xbbc93d7f,0xbcdbbd67,
0x3d0e3d55,0xbd67bcdb,0x3d7fbbc9,0xbd4e3d18,0xbd800000,0x3d5cbd04,0xbcf13d62,0xbb49bd80,0xbd7b3c48,0x3d3ebd2c,0xbc953d75,0xbc79bd78,0x3cc4bd6d,0x3c163d7d,0xbd22bd46,0x3d713cac,
0x3cc43d6d,0xbd2cbd3e,0x3d623cf1,0xbd7dbc16,0x3d7bbc48,0xbd5c3d04,0x3d22bd46,0xbcac3d71,0xbd35bd35,0x3d673cdb,0xbd7fbbc9,0x3d78bc79,0xbd553d0e,0x3d18bd4e,0xbc953d75,0xbb49bd80,
0x3d6d3cc4,0xbd80bb49,0x3d75bc95,0xbd4e3d18,0x3d0ebd55,0xbc793d78,0xbbc9bd7f,0x3cdb3d67,0xbd800000,0x3d71bcac,0xbd463d22,0x3d04bd5c,0xbc483d7b,0xbc16bd7d,0x3cf13d62,0xbd3ebd2c,
0x3d0ebd55,0xbcdb3d67,0x3c95bd75,0xbc163d7d,0x3d6dbcc4,0xbd5c3d04,0x3d46bd22,0xbd2c3d3e,0x3d7b3c48,0xbd80bb49,0x3d7fbbc9,0xbd783c79,0x3d353d35,0xbd4ebd18,0x3d623cf1,0xbd71bcac,
0x3c483d7b,0xbcacbd71,0x3cf13d62,0xbd18bd4e,0xbcc43d6d,0x3c79bd78,0xbbc93d7f,0xbb49bd80,0xbd553d0e,0x3d3ebd2c,0xbd223d46,0x3d04bd5c,0xbd800000,0x3d7dbc16,0xbd753c95,0x3d67bcdb,
0x3d80,0x3b49bd80,0xbbc93d7f,0x3c16bd7d,0xbc483d7b,0x3c79bd78,0xbc953d75,0x3cacbd71,0xbcc43d6d,0x3cdbbd67,0xbcf13d62,0x3d04bd5c,0xbd0e3d55,0x3d18bd4e,0xbd223d46,0x3d2cbd3e,
0xbd353d35,0x3d3ebd2c,0xbd463d22,0x3d4ebd18,0xbd553d0e,0x3d5cbd04,0xbd623cf1,0x3d67bcdb,0xbd6d3cc4,0x3d71bcac,0xbd753c95,0x3d78bc79,0xbd7b3c48,0x3d7dbc16,0xbd7f3bc9,0x3d80bb49,
0xbd553d0e,0x3d71bcac,0xbd7f3bc9,0x3d7d3c16,0x3d80,0x3c79bd78,0xbcf13d62,0x3d2cbd3e,0xbc48bd7b,0xbb493d80,0x3c95bd75,0xbd043d5c,0xbd6dbcc4,0x3d4e3d18,0xbd22bd46,0x3cdb3d67,
0x3d7b3c48,0xbd67bcdb,0x3d463d22,0xbd18bd4e,0x3d35bd35,0xbd5c3d04,0x3d75bc95,0xbd803b49,0xbd0e3d55,0x3d3ebd2c,0xbd623cf1,0x3d78bc79,0x3cc43d6d,0xbc16bd7d,0xbbc93d7f,0x3cacbd71,
0x3cc4bd6d,0xbd3e3d2c,0x3d75bc95,0xbd7dbc16,0x3d553d0e,0xbd04bd5c,0x3bc93d7f,0x3cacbd71,0x3d80,0x3cdbbd67,0xbd463d22,0x3d78bc79,0xbd7bbc48,0x3d4e3d18,0xbcf1bd62,0x3b493d80,
0x3d6dbcc4,0xbd80bb49,0x3d623cf1,0xbd18bd4e,0x3c483d7b,0x3c79bd78,0xbd223d46,0x3d67bcdb,0xbd353d35,0x3d71bcac,0xbd7fbbc9,0x3d5c3d04,0xbd0ebd55,0x3c163d7d,0x3c95bd75,0xbd2c3d3e,
0xbd7b3c48,0x3d673cdb,0xbcf1bd62,0xbc163d7d,0x3d6d3cc4,0xbd04bd5c,0xbbc93d7f,0x3d2cbd3e,0xbd0ebd55,0xbb493d80,0x3d22bd46,0xbd783c79,0x3d80,0x3d18bd4e,0xbd753c95,0x3d713cac,
0x3d553d0e,0xbcacbd71,0xbc953d75,0x3d4ebd18,0xbcc4bd6d,0xbc793d78,0x3d46bd22,0xbd803b49,0xbc483d7b,0x3d3ebd2c,0xbd7f3bc9,0x3d5c3d04,0x3d35bd35,0xbd7d3c16,0x3d623cf1,0xbcdbbd67,
0xbd353d35,0x3d803b49,0xbd22bd46,0xbc163d7d,0x3d55bd0e,0xbd78bc79,0x3cf13d62,0x3cacbd71,0xbd6d3cc4,0x3d673cdb,0xbc95bd75,0xbd043d5c,0x3d7bbc48,0xbd4ebd18,0x3bc93d7f,0x3d2cbd3e,
0x3d80,0x3d3ebd2c,0xbd7fbbc9,0x3d183d4e,0x3c48bd7b,0xbd5c3d04,0x3d753c95,0xbcdbbd67,0xbcc43d6d,0x3d71bcac,0xbd62bcf1,0x3c793d78,0x3d0ebd55,0xbd7d3c16,0x3d463d22,0xbb49bd80,
0xbd7bbc48,0x3cac3d71,0x3d22bd46,0xbd7dbc16,0x3d35bd35,0xbd78bc79,0x3c953d75,0x3d2cbd3e,0x3d0ebd55,0xbd80bb49,0x3cf13d62,0x3d04bd5c,0x3cc43d6d,0x3d18bd4e,0xbd7fbbc9,0x3cdb3d67,
0x3d55bd0e,0xbd67bcdb,0x3bc93d7f,0x3d4ebd18,0x3d80,0x3d5cbd04,0xbd62bcf1,0x3b493d80,0x3c483d7b,0x3d3ebd2c,0xbd75bc95,0x3c793d78,0xbd6dbcc4,0x3c163d7d,0x3d46bd22,0xbd71bcac,
0x3d6dbcc4,0xbd2cbd3e,0xbcf13d62,0x3d7d3c16,0xbc48bd7b,0xbd5c3d04,0x3d463d22,0x3cacbd71,0xbd353d35,0x3d673cdb,0x3bc9bd7f,0xbd783c79,0x3d0e3d55,0x3d18bd4e,0xbd75bc95,0x3b493d80,
0x3cc4bd6d,0xbd80bb49,0x3c953d75,0x3d4ebd18,0xbd55bd0e,0xbc793d78,0x3d7fbbc9,0xbcdbbd67,0x3d80,0x3d71bcac,0xbd22bd46,0xbd043d5c,0x3d7b3c48,0xbc16bd7d,0xbd623cf1,0x3d3e3d2c,
0xbd55bd0e,0xbcdb3d67,0x3d753c95,0x3c16bd7d,0xbcc4bd6d,0xbd5c3d04,0x3d223d46,0x3d2cbd3e,0x3c48bd7b,0xbd80bb49,0x3bc93d7f,0x3d78bc79,0x3d35bd35,0xbd4ebd18,0xbcf13d62,0x3d713cac,
0x3d7bbc48,0xbcacbd71,0xbd623cf1,0x3d183d4e,0x3d6d3cc4,0x3c79bd78,0xbd7fbbc9,0x3b493d80,0x3d0e3d55,0x3d3ebd2c,0xbd46bd22,0xbd043d5c,0x3d80,0x3d7dbc16,0xbc95bd75,0xbd673cdb,
0xbd800000,0x3d803b49,0xbd7fbbc9,0x3d7d3c16,0xbd7bbc48,0x3d783c79,0xbd75bc95,0x3d713cac,0xbd6dbcc4,0x3d673cdb,0xbd62bcf1,0x3d5c3d04,0xbd55bd0e,0x3d4e3d18,0xbd46bd22,0x3d3e3d2c,
0xbd35bd35,0x3d2c3d3e,0xbd22bd46,0x3d183d4e,0xbd0ebd55,0x3d043d5c,0xbcf1bd62,0x3cdb3d67,0xbcc4bd6d,0x3cac3d71,0xbc95bd75,0x3c793d78,0xbc48bd7b,0x3c163d7d,0xbbc9bd7f,0x3b493d80,
0xbd0ebd55,0x3cac3d71,0xbbc9bd7f,0xbc163d7d,0xbd800000,0x3d783c79,0xbd62bcf1,0x3d3e3d2c,0x3d7bbc48,0xbd80bb49,0x3d753c95,0xbd5cbd04,0x3cc4bd6d,0xbd183d4e,0x3d46bd22,0xbd673cdb,
0xbc483d7b,0x3cdbbd67,0xbd223d46,0x3d4ebd18,0x3d353d35,0xbd04bd5c,0x3c953d75,0xbb49bd80,0xbd55bd0e,0x3d2c3d3e,0xbcf1bd62,0x3c793d78,0xbd6d3cc4,0x3d7dbc16,0xbd7fbbc9,0x3d713cac,
0x3d6d3cc4,0xbd2cbd3e,0x3c953d75,0x3c16bd7d,0xbd0e3d55,0x3d5cbd04,0xbd7f3bc9,0x3d713cac,0xbd800000,0x3d673cdb,0xbd22bd46,0x3c793d78,0x3c48bd7b,0xbd183d4e,0x3d62bcf1,0xbd803b49,
0x3cc43d6d,0x3b49bd80,0xbcf13d62,0x3d4ebd18,0xbd7b3c48,0x3d783c79,0xbd46bd22,0x3cdb3d67,0xbd35bd35,0x3cac3d71,0x3bc9bd7f,0xbd043d5c,0x3d55bd0e,0xbd7d3c16,0x3d753c95,0xbd3ebd2c,
0xbc48bd7b,0xbcdb3d67,0x3d62bcf1,0xbd7dbc16,0xbcc43d6d,0x3d5cbd04,0xbd7fbbc9,0x3d3e3d2c,0x3d55bd0e,0xbd80bb49,0x3d463d22,0xbc79bd78,0xbd800000,0x3d4e3d18,0xbc95bd75,0xbcac3d71,
0xbd0e3d55,0x3d71bcac,0xbd75bc95,0x3d183d4e,0x3d6dbcc4,0xbd78bc79,0x3d223d46,0xbb49bd80,0xbd7bbc48,0x3d2c3d3e,0xbbc9bd7f,0xbd043d5c,0x3d353d35,0xbc16bd7d,0xbcf13d62,0x3d67bcdb,
0xbd35bd35,0xbb493d80,0x3d46bd22,0xbd7dbc16,0x3d0e3d55,0x3c79bd78,0xbd623cf1,0x3d713cac,0xbcc4bd6d,0xbcdb3d67,0x3d75bc95,0xbd5cbd04,0x3c483d7b,0x3d18bd4e,0xbd7f3bc9,0x3d3e3d2c,
0xbd800000,0x3d2c3d3e,0x3bc9bd7f,0xbd4e3d18,0x3d7b3c48,0xbd04bd5c,0xbc953d75,0x3d67bcdb,0xbd6dbcc4,0x3cac3d71,0x3cf1bd62,0xbd783c79,0x3d553d0e,0xbc16bd7d,0xbd223d46,0x3d80bb49,
0x3c48bd7b,0xbd713cac,0x3d463d22,0x3c16bd7d,0x3d353d35,0x3c79bd78,0xbd753c95,0x3d3e3d2c,0x3d553d0e,0x3b49bd80,0xbd623cf1,0x3d5c3d04,0xbd6d3cc4,0x3d4e3d18,0x3bc9bd7f,0xbd673cdb,
0x3d0e3d55,0x3cdbbd67,0xbd7f3bc9,0x3d183d4e,0xbd800000,0x3d043d5c,0x3cf1bd62,0xbd803b49,0xbd7b3c48,0x3d2c3d3e,0x3c95bd75,0xbd783c79,0x3cc4bd6d,0xbd7d3c16,0x3d223d46,0x3cacbd71,
0x3cc43d6d,0x3d3ebd2c,0xbd62bcf1,0xbc163d7d,0x3d7bbc48,0xbd04bd5c,0xbd223d46,0x3d713cac,0xbd35bd35,0xbcdb3d67,0x3d7f3bc9,0xbc79bd78,0xbd553d0e,0x3d4e3d18,0x3c95bd75,0xbd803b49,
0x3d6d3cc4,0x3b49bd80,0xbd753c95,0x3d183d4e,0x3d0ebd55,0xbd78bc79,0x3bc93d7f,0x3d67bcdb,0xbd800000,0x3cac3d71,0x3d46bd22,0xbd5cbd04,0xbc483d7b,0x3d7dbc16,0xbcf1bd62,0xbd2c3d3e,
0x3d0ebd55,0xbd67bcdb,0xbc953d75,0x3d7d3c16,0x3d6dbcc4,0xbd04bd5c,0xbd463d22,0x3d3e3d2c,0x3d7b3c48,0x3b49bd80,0xbd7f3bc9,0x3c793d78,0x3d353d35,0x3d18bd4e,0xbd62bcf1,0xbcac3d71,
0x3c483d7b,0x3d71bcac,0xbcf1bd62,0xbd4e3d18,0xbcc43d6d,0x3d783c79,0x3bc9bd7f,0xbd803b49,0xbd553d0e,0x3d2c3d3e,0x3d22bd46,0xbd5cbd04,0xbd800000,0x3c163d7d,0x3d75bc95,0xbcdbbd67,
0x3d80,0x3d803b49,0x3bc9bd7f,0xbd7dbc16,0xbc483d7b,0x3d783c79,0x3c95bd75,0xbd71bcac,0xbcc43d6d,0x3d673cdb,0x3cf1bd62,0xbd5cbd04,0xbd0e3d55,0x3d4e3d18,0x3d22bd46,0xbd3ebd2c,
0xbd353d35,0x3d2c3d3e,0x3d46bd22,0xbd18bd4e,0xbd553d0e,0x3d043d5c,0x3d62bcf1,0xbcdbbd67,0xbd6d3cc4,0x3cac3d71,0x3d75bc95,0xbc79bd78,0xbd7b3c48,0x3c163d7d,0x3d7fbbc9,0xbb49bd80,
0xbd553d0e,0x3cac3d71,0x3d7fbbc9,0x3c16bd7d,0x3d80,0x3d783c79,0x3cf1bd62,0xbd3ebd2c,0xbc48bd7b,0xbd80bb49,0xbc953d75,0x3d5c3d04,0xbd6dbcc4,0xbd183d4e,0x3d223d46,0x3d67bcdb,
0x3d7b3c48,0x3cdbbd67,0xbd46bd22,0xbd4e3d18,0x3d35bd35,0xbd04bd5c,0xbd753c95,0x3b493d80,0xbd0e3d55,0x3d2c3d3e,0x3d62bcf1,0xbc79bd78,0x3cc43d6d,0x3d7dbc16,0x3bc9bd7f,0xbd71bcac,
0x3cc4bd6d,0xbd2cbd3e,0xbd753c95,0xbc163d7d,0x3d553d0e,0x3d5cbd04,0xbbc9bd7f,0xbd71bcac,0x3d80,0x3d673cdb,0x3d46bd22,0xbc79bd78,0xbd7bbc48,0xbd183d4e,0x3cf13d62,0x3d80bb49,
0x3d6dbcc4,0x3b49bd80,0xbd62bcf1,0xbd4e3d18,0x3c483d7b,0x3d783c79,0x3d22bd46,0xbcdbbd67,0xbd353d35,0x3cac3d71,0x3d7f3bc9,0x3d04bd5c,0xbd0ebd55,0xbd7d3c16,0xbc953d75,0x3d3e3d2c,
0xbd7b3c48,0xbcdb3d67,0x3cf13d62,0x3d7d3c16,0x3d6d3cc4,0x3d5cbd04,0x3bc9bd7f,0xbd3ebd2c,0xbd0ebd55,0xbd80bb49,0xbd223d46,0x3c793d78,0x3d80,0x3d4e3d18,0x3d75bc95,0x3cacbd71,
0x3d553d0e,0x3d71bcac,0x3c95bd75,0xbd18bd4e,0xbcc4bd6d,0xbd78bc79,0xbd463d22,0x3b493d80,0xbc483d7b,0x3d2c3d3e,0x3d7fbbc9,0x3d04bd5c,0x3d35bd35,0xbc16bd7d,0xbd62bcf1,0xbd673cdb,
0xbd353d35,0xbb493d80,0x3d223d46,0x3d7d3c16,0x3d55bd0e,0x3c79bd78,0xbcf1bd62,0xbd71bcac,0xbd6d3cc4,0xbcdb3d67,0x3c953d75,0x3d5c3d04,0x3d7bbc48,0x3d18bd4e,0xbbc9bd7f,0xbd3ebd2c,
0x3d80,0x3d2c3d3e,0x3d7f3bc9,0x3d4ebd18,0x3c48bd7b,0xbd04bd5c,0xbd75bc95,0xbd673cdb,0xbcc43d6d,0x3cac3d71,0x3d623cf1,0x3d78bc79,0x3d0ebd55,0xbc16bd7d,0xbd46bd22,0xbd803b49,
0xbd7bbc48,0xbd713cac,0xbd223d46,0xbc163d7d,0x3d35bd35,0x3c79bd78,0xbc95bd75,0xbd3ebd2c,0x3d0ebd55,0x3b49bd80,0xbcf1bd62,0xbd5cbd04,0x3cc43d6d,0x3d4e3d18,0x3d7f3bc9,0x3d67bcdb,
0x3d55bd0e,0x3cdbbd67,0xbbc9bd7f,0xbd18bd4e,0x3d80,0x3d043d5c,0x3d623cf1,0x3d80bb49,0x3c483d7b,0x3d2c3d3e,0x3d753c95,0x3d78bc79,0xbd6dbcc4,0xbd7d3c16,0xbd463d22,0xbcac3d71,
0x3d6dbcc4,0x3d3ebd2c,0x3cf1bd62,0x3c16bd7d,0xbc48bd7b,0xbd04bd5c,0xbd46bd22,0xbd71bcac,0xbd353d35,0xbcdb3d67,0xbbc93d7f,0x3c793d78,0x3d0e3d55,0x3d4e3d18,0x3d753c95,0x3d80bb49,
0x3cc4bd6d,0x3b49bd80,0xbc95bd75,0xbd18bd4e,0xbd55bd0e,0xbd78bc79,0xbd7f3bc9,0xbd673cdb,0x3d80,0x3cac3d71,0x3d223d46,0x3d5c3d04,0x3d7b3c48,0x3d7dbc16,0x3d62bcf1,0x3d2cbd3e,
0xbd55bd0e,0xbd67bcdb,0xbd75bc95,0xbd7dbc16,0xbcc4bd6d,0xbd04bd5c,0xbd22bd46,0xbd3ebd2c,0x3c48bd7b,0x3b49bd80,0xbbc9bd7f,0xbc79bd78,0x3d35bd35,0x3d18bd4e,0x3cf1bd62,0x3cacbd71,
0x3d7bbc48,0x3d71bcac,0x3d62bcf1,0x3d4ebd18,0x3d6d3cc4,0x3d783c79,0x3d7f3bc9,0x3d80bb49,0x3d0e3d55,0x3d2c3d3e,0x3d463d22,0x3d5c3d04,0x3d80,0x3c163d7d,0x3c953d75,0x3cdb3d67,
0xbd800000,0xbb493d80,0x3d7f3bc9,0x3c16bd7d,0xbd7bbc48,0xbc793d78,0x3d753c95,0x3cacbd71,0xbd6dbcc4,0xbcdb3d67,0x3d623cf1,0x3d04bd5c,0xbd55bd0e,0xbd183d4e,0x3d463d22,0x3d2cbd3e,
0xbd35bd35,0xbd3e3d2c,0x3d223d46,0x3d4ebd18,0xbd0ebd55,0xbd5c3d04,0x3cf13d62,0x3d67bcdb,0xbcc4bd6d,0xbd713cac,0x3c953d75,0x3d78bc79,0xbc48bd7b,0xbd7d3c16,0x3bc93d7f,0x3d80bb49,
0xbd0ebd55,0xbd713cac,0x3bc93d7f,0x3d7d3c16,0xbd800000,0xbc793d78,0x3d623cf1,0x3d2cbd3e,0x3d7bbc48,0x3b49bd80,0xbd75bc95,0xbd043d5c,0x3cc4bd6d,0xbd4ebd18,0xbd463d22,0x3cdb3d67,
0xbc483d7b,0x3d673cdb,0x3d22bd46,0xbd18bd4e,0x3d353d35,0x3d5cbd04,0xbc95bd75,0xbd803b49,0xbd55bd0e,0xbd3e3d2c,0x3cf13d62,0x3d78bc79,0xbd6d3cc4,0x3c163d7d,0x3d7f3bc9,0x3cacbd71,
0x3d6d3cc4,0x3d3ebd2c,0xbc95bd75,0xbd7dbc16,0xbd0e3d55,0x3d043d5c,0x3d7fbbc9,0x3cacbd71,0xbd800000,0xbcdb3d67,0x3d223d46,0x3d78bc79,0x3c48bd7b,0xbd4ebd18,0xbd623cf1,0x3b493d80,
0x3cc43d6d,0x3d803b49,0x3cf1bd62,0xbd18bd4e,0xbd7b3c48,0xbc793d78,0x3d463d22,0x3d67bcdb,0xbd35bd35,0xbd713cac,0xbbc93d7f,0x3d5c3d04,0x3d55bd0e,0xbc16bd7d,0xbd75bc95,0xbd2c3d3e,
0xbc48bd7b,0xbd67bcdb,0xbd623cf1,0xbc163d7d,0xbcc43d6d,0x3d043d5c,0x3d7f3bc9,0x3d2cbd3e,0x3d55bd0e,0x3b49bd80,0xbd46bd22,0xbd783c79,0xbd800000,0xbd183d4e,0x3c953d75,0x3d713cac,
0xbd0e3d55,0x3cac3d71,0x3d753c95,0x3d4ebd18,0x3d6dbcc4,0x3c79bd78,0xbd22bd46,0xbd803b49,0xbd7bbc48,0xbd3e3d2c,0x3bc93d7f,0x3d5c3d04,0x3d353d35,0x3d7dbc16,0x3cf1bd62,0xbcdbbd67,
0xbd35bd35,0xbd80bb49,0xbd463d22,0xbc163d7d,0x3d0e3d55,0x3d783c79,0x3d62bcf1,0x3cacbd71,0xbcc4bd6d,0xbd67bcdb,0xbd753c95,0xbd043d5c,0x3c483d7b,0x3d4e3d18,0x3d7fbbc9,0x3d2cbd3e,
0xbd800000,0xbd3e3d2c,0xbbc93d7f,0x3d183d4e,0x3d7b3c48,0x3d5cbd04,0x3c95bd75,0xbcdbbd67,0xbd6dbcc4,0xbd713cac,0xbcf13d62,0x3c793d78,0x3d553d0e,0x3d7dbc16,0x3d22bd46,0xbb49bd80,
0x3c48bd7b,0xbcacbd71,0xbd46bd22,0xbd7dbc16,0x3d353d35,0x3d783c79,0x3d75bc95,0x3d2cbd3e,0x3d553d0e,0x3d803b49,0x3d62bcf1,0x3d04bd5c,0xbd6d3cc4,0xbd183d4e,0xbbc93d7f,0x3cdb3d67,
0x3d0e3d55,0x3d673cdb,0x3d7fbbc9,0x3d4ebd18,0xbd800000,0xbd5c3d04,0xbcf13d62,0x3b493d80,0xbd7b3c48,0xbd3e3d2c,0xbc953d75,0x3c793d78,0x3cc4bd6d,0xbc16bd7d,0xbd22bd46,0xbd71bcac,
0x3cc43d6d,0x3d2c3d3e,0x3d623cf1,0x3d7d3c16,0x3d7bbc48,0x3d5cbd04,0x3d22bd46,0x3cacbd71,0xbd35bd35,0xbd67bcdb,0xbd7fbbc9,0xbd783c79,0xbd553d0e,0xbd183d4e,0xbc953d75,0x3b493d80,
0x3d6d3cc4,0x3d803b49,0x3d75bc95,0x3d4ebd18,0x3d0ebd55,0x3c79bd78,0xbbc9bd7f,0xbcdbbd67,0xbd800000,0xbd713cac,0xbd463d22,0xbd043d5c,0xbc483d7b,0x3c163d7d,0x3cf13d62,0x3d3e3d2c,
0x3d0ebd55,0x3cdbbd67,0x3c95bd75,0x3c16bd7d,0x3d6dbcc4,0x3d5cbd04,0x3d46bd22,0x3d2cbd3e,0x3d7b3c48,0x3d803b49,0x3d7fbbc9,0x3d78bc79,0x3d353d35,0x3d4e3d18,0x3d623cf1,0x3d713cac,
0x3c483d7b,0x3cac3d71,0x3cf13d62,0x3d183d4e,0xbcc43d6d,0xbc793d78,0xbbc93d7f,0x3b493d80,0xbd553d0e,0xbd3e3d2c,0xbd223d46,0xbd043d5c,0xbd800000,0xbd7d3c16,0xbd753c95,0xbd673cdb,
0x3d80,0xbbc93d7f,0xbc483d7b,0xbc953d75,0xbcc43d6d,0xbcf13d62,0xbd0e3d55,0xbd223d46,0xbd353d35,0xbd463d22,0xbd553d0e,0xbd623cf1,0xbd6d3cc4,0xbd753c95,0xbd7b3c48,0xbd7f3bc9,
0xbd800000,0xbd7fbbc9,0xbd7bbc48,0xbd75bc95,0xbd6dbcc4,0xbd62bcf1,0xbd55bd0e,0xbd46bd22,0xbd35bd35,0xbd22bd46,0xbd0ebd55,0xbcf1bd62,0xbcc4bd6d,0xbc95bd75,0xbc48bd7b,0xbbc9bd7f,
0xbd6d3cc4,0xbd7f3bc9,0xbd7bbc48,0xbd62bcf1,0x3d80,0xbc953d75,0xbd0e3d55,0xbd463d22,0x3cc4bd6d,0x3d22bd46,0x3d55bd0e,0x3d75bc95,0xbd35bd35,0xbcf1bd62,0xbc48bd7b,0x3bc9bd7f,
0x3cc43d6d,0x3bc93d7f,0xbc483d7b,0xbcf13d62,0x3d800000,0x3d753c95,0x3d553d0e,0x3d223d46,0xbd6dbcc4,0xbd46bd22,0xbd0ebd55,0xbc95bd75,0xbd353d35,0xbd623cf1,0xbd7b3c48,0xbd7fbbc9,
0x3d35bd35,0x3d75bc95,0x3d7b3c48,0x3d463d22,0x3cc43d6d,0xbbc93d7f,0xbd0e3d55,0xbd623cf1,0x3d80,0xbcf13d62,0xbd553d0e,0xbd7f3bc9,0xbd6dbcc4,0xbd22bd46,0xbc48bd7b,0x3c95bd75,
0x3d353d35,0x3c953d75,0xbc483d7b,0xbd223d46,0xbd6d3cc4,0xbd7fbbc9,0xbd55bd0e,0xbcf1bd62,0xbd800000,0xbd62bcf1,0xbd0ebd55,0xbbc9bd7f,0x3cc4bd6d,0x3d46bd22,0x3d7bbc48,0x3d753c95,
0xbd6dbcc4,0xbcf1bd62,0x3c48bd7b,0x3d46bd22,0x3d353d35,0x3bc93d7f,0xbd0e3d55,0xbd753c95,0xbcc4bd6d,0x3c95bd75,0x3d55bd0e,0x3d7f3bc9,0x3d80,0xbd223d46,0xbd7b3c48,0xbd62bcf1,
0xbcc43d6d,0xbd623cf1,0xbd7bbc48,0xbd22bd46,0x3d35bd35,0x3d7fbbc9,0x3d553d0e,0x3c953d75,0xbd6d3cc4,0xbd75bc95,0xbd0ebd55,0x3bc9bd7f,0x3d800000,0x3d463d22,0x3c483d7b,0xbcf13d62,
0xbd800000,0xbd22bd46,0x3c48bd7b,0x3d62bcf1,0x3d6d3cc4,0x3c953d75,0xbd0e3d55,0xbd7f3bc9,0xbd35bd35,0x3bc9bd7f,0x3d55bd0e,0x3d753c95,0x3cc43d6d,0xbcf13d62,0xbd7b3c48,0xbd46bd22,
0x3d80,0xbd463d22,0xbd7bbc48,0xbcf1bd62,0x3cc4bd6d,0x3d75bc95,0x3d553d0e,0x3bc93d7f,0xbd353d35,0xbd7fbbc9,0xbd0ebd55,0x3c95bd75,0x3d6dbcc4,0x3d623cf1,0x3c483d7b,0xbd223d46,
0xbcc4bd6d,0x3d22bd46,0x3d7b3c48,0x3c953d75,0x3d800000,0x3cf13d62,0xbd0e3d55,0xbd7fbbc9,0x3d6d3cc4,0x3bc93d7f,0xbd553d0e,0xbd62bcf1,0xbd353d35,0xbd75bc95,0xbc48bd7b,0x3d46bd22,
0x3d6dbcc4,0x3d463d22,0xbc483d7b,0xbd753c95,0x3d80,0xbd623cf1,0xbd55bd0e,0x3bc9bd7f,0xbcc43d6d,0xbd7f3bc9,0xbd0ebd55,0x3cf1bd62,0xbd35bd35,0x3c95bd75,0x3d7bbc48,0x3d223d46,
0x3d353d35,0xbcf13d62,0xbd7bbc48,0xbbc9bd7f,0x3d6dbcc4,0x3d223d46,0xbd0e3d55,0xbd75bc95,0xbd800000,0xbc95bd75,0x3d55bd0e,0x3d463d22,0xbcc43d6d,0xbd7fbbc9,0xbc48bd7b,0x3d62bcf1,
0x3d35bd35,0x3d623cf1,0xbc483d7b,0xbd7f3bc9,0xbcc4bd6d,0x3d46bd22,0x3d553d0e,0xbc953d75,0x3d80,0xbd753c95,0xbd0ebd55,0x3d22bd46,0x3d6d3cc4,0xbbc93d7f,0xbd7b3c48,0xbcf1bd62,
0x3cc4bd6d,0x3d753c95,0xbc483d7b,0xbd7fbbc9,0x3d35bd35,0x3d463d22,0xbd0e3d55,0xbd62bcf1,0x3d6dbcc4,0x3cf13d62,0xbd553d0e,0xbd22bd46,0x3d800000,0x3bc93d7f,0xbd7b3c48,0xbc95bd75,
0x3d6d3cc4,0xbc953d75,0xbd7bbc48,0x3bc9bd7f,0x3d353d35,0xbd223d46,0xbd55bd0e,0x3cf1bd62,0x3cc43d6d,0xbd623cf1,0xbd0ebd55,0x3d46bd22,0x3d80,0xbd7f3bc9,0xbc48bd7b,0x3d75bc95,
0xbd800000,0xbd7fbbc9,0xbd7bbc48,0xbd75bc95,0xbd6dbcc4,0xbd62bcf1,0xbd55bd0e,0xbd46bd22,0xbd35bd35,0xbd22bd46,0xbd0ebd55,0xbcf1bd62,0xbcc4bd6d,0xbc95bd75,0xbc48bd7b,0xbbc9bd7f,
0x8000bd80,0x3bc9bd7f,0x3c48bd7b,0x3c95bd75,0x3cc4bd6d,0x3cf1bd62,0x3d0ebd55,0x3d22bd46,0x3d35bd35,0x3d46bd22,0x3d55bd0e,0x3d62bcf1,0x3d6dbcc4,0x3d75bc95,0x3d7bbc48,0x3d7fbbc9,
0xbcc4bd6d,0xbbc9bd7f,0x3c48bd7b,0x3cf1bd62,0xbd800000,0xbd75bc95,0xbd55bd0e,0xbd22bd46,0x3d6d3cc4,0x3d463d22,0x3d0e3d55,0x3c953d75,0x3d35bd35,0x3d62bcf1,0x3d7bbc48,0x3d7f3bc9,
0xbd6d3cc4,0xbd7f3bc9,0xbd7bbc48,0xbd62bcf1,0x80003d80,0xbc953d75,0xbd0e3d55,0xbd463d22,0x3cc4bd6d,0x3d22bd46,0x3d55bd0e,0x3d75bc95,0xbd35bd35,0xbcf1bd62,0xbc48bd7b,0x3bc9bd7f,
0x3d353d35,0x3c953d75,0xbc483d7b,0xbd223d46,0xbd6d3cc4,0xbd7fbbc9,0xbd55bd0e,0xbcf1bd62,0xbd800000,0xbd62bcf1,0xbd0ebd55,0xbbc9bd7f,0x3cc4bd6d,0x3d46bd22,0x3d7bbc48,0x3d753c95,
0xbd353d35,0xbd753c95,0xbd7bbc48,0xbd46bd22,0xbcc4bd6d,0x3bc9bd7f,0x3d0ebd55,0x3d62bcf1,0x8000bd80,0x3cf1bd62,0x3d55bd0e,0x3d7fbbc9,0x3d6d3cc4,0x3d223d46,0x3c483d7b,0xbc953d75,
0x3cc4bd6d,0x3d62bcf1,0x3d7b3c48,0x3d223d46,0xbd353d35,0xbd7f3bc9,0xbd55bd0e,0xbc95bd75,0x3d6dbcc4,0x3d753c95,0x3d0e3d55,0xbbc93d7f,0xbd800000,0xbd46bd22,0xbc48bd7b,0x3cf1bd62,
0xbd6dbcc4,0xbcf1bd62,0x3c48bd7b,0x3d46bd22,0x3d353d35,0x3bc93d7f,0xbd0e3d55,0xbd753c95,0xbcc4bd6d,0x3c95bd75,0x3d55bd0e,0x3d7f3bc9,0x80003d80,0xbd223d46,0xbd7b3c48,0xbd62bcf1,
0x8000bd80,0x3d46bd22,0x3d7b3c48,0x3cf13d62,0xbcc43d6d,0xbd753c95,0xbd55bd0e,0xbbc9bd7f,0x3d35bd35,0x3d7f3bc9,0x3d0e3d55,0xbc953d75,0xbd6d3cc4,0xbd62bcf1,0xbc48bd7b,0x3d22bd46,
0xbd800000,0xbd22bd46,0x3c48bd7b,0x3d62bcf1,0x3d6d3cc4,0x3c953d75,0xbd0e3d55,0xbd7f3bc9,0xbd35bd35,0x3bc9bd7f,0x3d55bd0e,0x3d753c95,0x3cc43d6d,0xbcf13d62,0xbd7b3c48,0xbd46bd22,
0x3d6dbcc4,0x3d463d22,0xbc483d7b,0xbd753c95,0x80003d80,0xbd623cf1,0xbd55bd0e,0x3bc9bd7f,0xbcc43d6d,0xbd7f3bc9,0xbd0ebd55,0x3cf1bd62,0xbd35bd35,0x3c95bd75,0x3d7bbc48,0x3d223d46,
0x3cc43d6d,0xbd223d46,0xbd7bbc48,0xbc95bd75,0xbd800000,0xbcf1bd62,0x3d0ebd55,0x3d7f3bc9,0xbd6dbcc4,0xbbc9bd7f,0x3d55bd0e,0x3d623cf1,0x3d35bd35,0x3d753c95,0x3c483d7b,0xbd463d22,
0xbd353d35,0xbd62bcf1,0x3c48bd7b,0x3d7fbbc9,0x3cc43d6d,0xbd463d22,0xbd55bd0e,0x3c95bd75,0x8000bd80,0x3d75bc95,0x3d0e3d55,0xbd223d46,0xbd6dbcc4,0x3bc9bd7f,0x3d7bbc48,0x3cf13d62,
0x3d353d35,0xbcf13d62,0xbd7bbc48,0xbbc9bd7f,0x3d6dbcc4,0x3d223d46,0xbd0e3d55,0xbd75bc95,0xbd800000,0xbc95bd75,0x3d55bd0e,0x3d463d22,0xbcc43d6d,0xbd7fbbc9,0xbc48bd7b,0x3d62bcf1,
0x3d6d3cc4,0xbc953d75,0xbd7bbc48,0x3bc9bd7f,0x3d353d35,0xbd223d46,0xbd55bd0e,0x3cf1bd62,0x3cc43d6d,0xbd623cf1,0xbd0ebd55,0x3d46bd22,0x80003d80,0xbd7f3bc9,0xbc48bd7b,0x3d75bc95,
0xbcc43d6d,0xbd75bc95,0x3c48bd7b,0x3d7f3bc9,0xbd353d35,0xbd46bd22,0x3d0ebd55,0x3d623cf1,0xbd6d3cc4,0xbcf1bd62,0x3d55bd0e,0x3d223d46,0xbd800000,0xbbc9bd7f,0x3d7bbc48,0x3c953d75,
0x3d80,0xbd7fbbc9,0x3c48bd7b,0x3d753c95,0xbcc43d6d,0xbd62bcf1,0x3d0ebd55,0x3d463d22,0xbd353d35,0xbd22bd46,0x3d55bd0e,0x3cf13d62,0xbd6d3cc4,0xbc95bd75,0x3d7bbc48,0x3bc93d7f,
0xbd800000,0x3bc9bd7f,0x3d7b3c48,0xbc953d75,0xbd6dbcc4,0x3cf1bd62,0x3d553d0e,0xbd223d46,0xbd35bd35,0x3d46bd22,0x3d0e3d55,0xbd623cf1,0xbcc4bd6d,0x3d75bc95,0x3c483d7b,0xbd7f3bc9,
0xbd6d3cc4,0xbbc9bd7f,0x3d7b3c48,0xbcf13d62,0x3d80,0xbd75bc95,0x3d0ebd55,0x3d223d46,0x3cc4bd6d,0x3d463d22,0xbd553d0e,0xbc95bd75,0xbd35bd35,0x3d62bcf1,0x3c483d7b,0xbd7fbbc9,
0x3cc43d6d,0xbd7f3bc9,0x3c48bd7b,0x3d623cf1,0x3d800000,0xbc953d75,0xbd55bd0e,0x3d46bd22,0xbd6dbcc4,0x3d22bd46,0x3d0e3d55,0xbd753c95,0xbd353d35,0xbcf1bd62,0x3d7bbc48,0xbbc93d7f,
0x3d35bd35,0x3c953d75,0xbd7bbc48,0x3d22bd46,0x3cc43d6d,0xbd7fbbc9,0x3d0ebd55,0x3cf13d62,0x3d80,0xbd62bcf1,0x3d55bd0e,0x3bc93d7f,0xbd6dbcc4,0x3d46bd22,0x3c483d7b,0xbd75bc95,
0x3d353d35,0xbd753c95,0x3c48bd7b,0x3d463d22,0xbd6d3cc4,0x3bc9bd7f,0x3d553d0e,0xbd623cf1,0xbd800000,0x3cf1bd62,0x3d0e3d55,0xbd7f3bc9,0x3cc4bd6d,0x3d223d46,0xbd7b3c48,0x3c95bd75,
0xbd6dbcc4,0x3d62bcf1,0xbc483d7b,0xbd22bd46,0x3d353d35,0xbd7f3bc9,0x3d0ebd55,0x3c953d75,0xbcc4bd6d,0x3d753c95,0xbd553d0e,0x3bc9bd7f,0x3d80,0xbd46bd22,0x3d7bbc48,0xbcf13d62,
0xbcc43d6d,0xbcf1bd62,0x3d7b3c48,0xbd463d22,0x3d35bd35,0x3bc93d7f,0xbd55bd0e,0x3d75bc95,0xbd6d3cc4,0x3c95bd75,0x3d0e3d55,0xbd7fbbc9,0x3d800000,0xbd223d46,0xbc48bd7b,0x3d623cf1,
0xbd800000,0x3d46bd22,0xbc483d7b,0xbcf1bd62,0x3d6d3cc4,0xbd753c95,0x3d0ebd55,0x3bc93d7f,0xbd35bd35,0x3d7f3bc9,0xbd553d0e,0x3c95bd75,0x3cc43d6d,0xbd62bcf1,0x3d7bbc48,0xbd223d46,
0x3d80,0xbd22bd46,0x3d7b3c48,0xbd623cf1,0x3cc4bd6d,0x3c953d75,0xbd55bd0e,0x3d7fbbc9,0xbd353d35,0x3bc9bd7f,0x3d0e3d55,0xbd75bc95,0x3d6dbcc4,0xbcf13d62,0xbc48bd7b,0x3d463d22,
0xbcc4bd6d,0x3d463d22,0xbd7bbc48,0x3d75bc95,0x3d800000,0xbd623cf1,0x3d0ebd55,0xbbc93d7f,0x3d6d3cc4,0xbd7f3bc9,0x3d55bd0e,0xbcf13d62,0xbd353d35,0x3c95bd75,0x3c483d7b,0xbd22bd46,
0x3d6dbcc4,0xbd223d46,0x3c48bd7b,0x3c953d75,0x3d80,0xbcf1bd62,0x3d553d0e,0xbd7fbbc9,0xbcc43d6d,0xbbc9bd7f,0x3d0e3d55,0xbd62bcf1,0xbd35bd35,0x3d753c95,0xbd7b3c48,0x3d46bd22,
0x3d353d35,0xbd62bcf1,0x3d7b3c48,0xbd7f3bc9,0x3d6dbcc4,0xbd463d22,0x3d0ebd55,0xbc953d75,0xbd800000,0x3d75bc95,0xbd553d0e,0x3d22bd46,0xbcc43d6d,0x3bc9bd7f,0x3c483d7b,0xbcf1bd62,
0x3d35bd35,0xbcf13d62,0x3c48bd7b,0x3bc93d7f,0xbcc4bd6d,0x3d223d46,0xbd55bd0e,0x3d753c95,0x3d80,0xbc95bd75,0x3d0e3d55,0xbd46bd22,0x3d6d3cc4,0xbd7fbbc9,0x3d7bbc48,0xbd623cf1,
0x3cc4bd6d,0xbc953d75,0x3c48bd7b,0xbbc93d7f,0x3d35bd35,0xbd223d46,0x3d0ebd55,0xbcf13d62,0x3d6dbcc4,0xbd623cf1,0x3d55bd0e,0xbd463d22,0x3d800000,0xbd7f3bc9,0x3d7bbc48,0xbd753c95,
0x3d6d3cc4,0xbd75bc95,0x3d7b3c48,0xbd7fbbc9,0x3d353d35,0xbd46bd22,0x3d553d0e,0xbd62bcf1,0x3cc43d6d,0xbcf1bd62,0x3d0e3d55,0xbd22bd46,0x3d80,0xbbc9bd7f,0x3c483d7b,0xbc95bd75,
0xbd800000,0x3bc9bd7f,0x3d7b3c48,0xbc953d75,0xbd6dbcc4,0x3cf1bd62,0x3d553d0e,0xbd223d46,0xbd35bd35,0x3d46bd22,0x3d0e3d55,0xbd623cf1,0xbcc4bd6d,0x3d75bc95,0x3c483d7b,0xbd7f3bc9,
0x8000bd80,0x3d7f3bc9,0xbc483d7b,0xbd75bc95,0x3cc4bd6d,0x3d623cf1,0xbd0e3d55,0xbd46bd22,0x3d35bd35,0x3d223d46,0xbd553d0e,0xbcf1bd62,0x3d6dbcc4,0x3c953d75,0xbd7b3c48,0xbbc9bd7f,
0xbcc4bd6d,0x3d7fbbc9,0xbc483d7b,0xbd62bcf1,0xbd800000,0x3c95bd75,0x3d553d0e,0xbd463d22,0x3d6d3cc4,0xbd223d46,0xbd0ebd55,0x3d75bc95,0x3d35bd35,0x3cf13d62,0xbd7b3c48,0x3bc9bd7f,
0xbd6d3cc4,0xbbc9bd7f,0x3d7b3c48,0xbcf13d62,0x80003d80,0xbd75bc95,0x3d0ebd55,0x3d223d46,0x3cc4bd6d,0x3d463d22,0xbd553d0e,0xbc95bd75,0xbd35bd35,0x3d62bcf1,0x3c483d7b,0xbd7fbbc9,
0x3d353d35,0xbd753c95,0x3c48bd7b,0x3d463d22,0xbd6d3cc4,0x3bc9bd7f,0x3d553d0e,0xbd623cf1,0xbd800000,0x3cf1bd62,0x3d0e3d55,0xbd7f3bc9,0x3cc4bd6d,0x3d223d46,0xbd7b3c48,0x3c95bd75,
0xbd353d35,0xbc95bd75,0x3d7b3c48,0xbd223d46,0xbcc4bd6d,0x3d7f3bc9,0xbd0e3d55,0xbcf1bd62,0x8000bd80,0x3d623cf1,0xbd553d0e,0xbbc9bd7f,0x3d6d3cc4,0xbd463d22,0xbc48bd7b,0x3d753c95,
0x3cc4bd6d,0x3cf13d62,0xbd7bbc48,0x3d46bd22,0xbd353d35,0xbbc9bd7f,0x3d553d0e,0xbd753c95,0x3d6dbcc4,0xbc953d75,0xbd0ebd55,0x3d7f3bc9,0xbd800000,0x3d22bd46,0x3c483d7b,0xbd62bcf1,
0xbd6dbcc4,0x3d62bcf1,0xbc483d7b,0xbd22bd46,0x3d353d35,0xbd7f3bc9,0x3d0ebd55,0x3c953d75,0xbcc4bd6d,0x3d753c95,0xbd553d0e,0x3bc9bd7f,0x80003d80,0xbd46bd22,0x3d7bbc48,0xbcf13d62,
0x8000bd80,0x3d223d46,0xbd7bbc48,0x3d62bcf1,0xbcc43d6d,0xbc95bd75,0x3d553d0e,0xbd7f3bc9,0x3d35bd35,0xbbc93d7f,0xbd0ebd55,0x3d753c95,0xbd6d3cc4,0x3cf1bd62,0x3c483d7b,0xbd46bd22,
0xbd800000,0x3d46bd22,0xbc483d7b,0xbcf1bd62,0x3d6d3cc4,0xbd753c95,0x3d0ebd55,0x3bc93d7f,0xbd35bd35,0x3d7f3bc9,0xbd553d0e,0x3c95bd75,0x3cc43d6d,0xbd62bcf1,0x3d7bbc48,0xbd223d46,
0x3d6dbcc4,0xbd223d46,0x3c48bd7b,0x3c953d75,0x80003d80,0xbcf1bd62,0x3d553d0e,0xbd7fbbc9,0xbcc43d6d,0xbbc9bd7f,0x3d0e3d55,0xbd62bcf1,0xbd35bd35,0x3d753c95,0xbd7b3c48,0x3d46bd22,
0x3cc43d6d,0xbd46bd22,0x3d7b3c48,0xbd753c95,0xbd800000,0x3d62bcf1,0xbd0e3d55,0x3bc9bd7f,0xbd6dbcc4,0x3d7fbbc9,0xbd553d0e,0x3cf1bd62,0x3d35bd35,0xbc953d75,0xbc48bd7b,0x3d223d46,
0xbd353d35,0x3cf1bd62,0xbc483d7b,0xbbc9bd7f,0x3cc43d6d,0xbd22bd46,0x3d553d0e,0xbd75bc95,0x8000bd80,0x3c953d75,0xbd0ebd55,0x3d463d22,0xbd6dbcc4,0x3d7f3bc9,0xbd7b3c48,0x3d62bcf1,
0x3d353d35,0xbd62bcf1,0x3d7b3c48,0xbd7f3bc9,0x3d6dbcc4,0xbd463d22,0x3d0ebd55,0xbc953d75,0xbd800000,0x3d75bc95,0xbd553d0e,0x3d22bd46,0xbcc43d6d,0x3bc9bd7f,0x3c483d7b,0xbcf1bd62,
0x3d6d3cc4,0xbd75bc95,0x3d7b3c48,0xbd7fbbc9,0x3d353d35,0xbd46bd22,0x3d553d0e,0xbd62bcf1,0x3cc43d6d,0xbcf1bd62,0x3d0e3d55,0xbd22bd46,0x80003d80,0xbbc9bd7f,0x3c483d7b,0xbc95bd75,
0xbcc43d6d,0x3c95bd75,0xbc483d7b,0x3bc9bd7f,0xbd353d35,0x3d22bd46,0xbd0e3d55,0x3cf1bd62,0xbd6d3cc4,0x3d62bcf1,0xbd553d0e,0x3d46bd22,0xbd800000,0x3d7fbbc9,0xbd7b3c48,0x3d75bc95,
0x3d80,0x3bc9bd7f,0xbc483d7b,0x3c95bd75,0xbcc43d6d,0x3cf1bd62,0xbd0e3d55,0x3d22bd46,0xbd353d35,0x3d46bd22,0xbd553d0e,0x3d62bcf1,0xbd6d3cc4,0x3d75bc95,0xbd7b3c48,0x3d7fbbc9,
0xbd800000,0x3d7f3bc9,0xbd7bbc48,0x3d753c95,0xbd6dbcc4,0x3d623cf1,0xbd55bd0e,0x3d463d22,0xbd35bd35,0x3d223d46,0xbd0ebd55,0x3cf13d62,0xbcc4bd6d,0x3c953d75,0xbc48bd7b,0x3bc93d7f,
0xbd6d3cc4,0x3d7fbbc9,0xbd7bbc48,0x3d623cf1,0x3d80,0x3c95bd75,0xbd0e3d55,0x3d46bd22,0x3cc4bd6d,0xbd223d46,0x3d55bd0e,0xbd753c95,0xbd35bd35,0x3cf13d62,0xbc48bd7b,0xbbc93d7f,
0x3cc43d6d,0xbbc9bd7f,0xbc483d7b,0x3cf1bd62,0x3d800000,0xbd75bc95,0x3d553d0e,0xbd22bd46,0xbd6dbcc4,0x3d463d22,0xbd0ebd55,0x3c953d75,0xbd353d35,0x3d62bcf1,0xbd7b3c48,0x3d7f3bc9,
0x3d35bd35,0xbd753c95,0x3d7b3c48,0xbd46bd22,0x3cc43d6d,0x3bc9bd7f,0xbd0e3d55,0x3d62bcf1,0x3d80,0x3cf1bd62,0xbd553d0e,0x3d7fbbc9,0xbd6dbcc4,0x3d223d46,0xbc48bd7b,0xbc953d75,
0x3d353d35,0xbc95bd75,0xbc483d7b,0x3d22bd46,0xbd6d3cc4,0x3d7f3bc9,0xbd55bd0e,0x3cf13d62,0xbd800000,0x3d623cf1,0xbd0ebd55,0x3bc93d7f,0x3cc4bd6d,0xbd463d22,0x3d7bbc48,0xbd75bc95,
0xbd6dbcc4,0x3cf13d62,0x3c48bd7b,0xbd463d22,0x3d353d35,0xbbc9bd7f,0xbd0e3d55,0x3d75bc95,0xbcc4bd6d,0xbc953d75,0x3d55bd0e,0xbd7fbbc9,0x3d80,0x3d22bd46,0xbd7b3c48,0x3d623cf1,
0xbcc43d6d,0x3d62bcf1,0xbd7bbc48,0x3d223d46,0x3d35bd35,0xbd7f3bc9,0x3d553d0e,0xbc95bd75,0xbd6d3cc4,0x3d753c95,0xbd0ebd55,0xbbc93d7f,0x3d800000,0xbd46bd22,0x3c483d7b,0x3cf1bd62,
0xbd800000,0x3d223d46,0x3c48bd7b,0xbd623cf1,0x3d6d3cc4,0xbc95bd75,0xbd0e3d55,0x3d7fbbc9,0xbd35bd35,0xbbc93d7f,0x3d55bd0e,0xbd75bc95,0x3cc43d6d,0x3cf1bd62,0xbd7b3c48,0x3d463d22,
0x3d80,0x3d46bd22,0xbd7bbc48,0x3cf13d62,0x3cc4bd6d,0xbd753c95,0x3d553d0e,0xbbc9bd7f,0xbd353d35,0x3d7f3bc9,0xbd0ebd55,0xbc953d75,0x3d6dbcc4,0xbd62bcf1,0x3c483d7b,0x3d22bd46,
0xbcc4bd6d,0xbd223d46,0x3d7b3c48,0xbc95bd75,0x3d800000,0xbcf1bd62,0xbd0e3d55,0x3d7f3bc9,0x3d6d3cc4,0xbbc9bd7f,0xbd553d0e,0x3d623cf1,0xbd353d35,0x3d753c95,0xbc48bd7b,0xbd463d22,
0x3d6dbcc4,0xbd46bd22,0xbc483d7b,0x3d75bc95,0x3d80,0x3d62bcf1,0xbd55bd0e,0xbbc93d7f,0xbcc43d6d,0x3d7fbbc9,0xbd0ebd55,0xbcf13d62,0xbd35bd35,0xbc953d75,0x3d7bbc48,0xbd22bd46,
0x3d353d35,0x3cf1bd62,0xbd7bbc48,0x3bc93d7f,0x3d6dbcc4,0xbd22bd46,0xbd0e3d55,0x3d753c95,0xbd800000,0x3c953d75,0x3d55bd0e,0xbd46bd22,0xbcc43d6d,0x3d7f3bc9,0xbc48bd7b,0xbd623cf1,
0x3d35bd35,0xbd62bcf1,0xbc483d7b,0x3d7fbbc9,0xbcc4bd6d,0xbd463d22,0x3d553d0e,0x3c95bd75,0x3d80,0x3d75bc95,0xbd0ebd55,0xbd223d46,0x3d6d3cc4,0x3bc9bd7f,0xbd7b3c48,0x3cf13d62,
0x3cc4bd6d,0xbd75bc95,0xbc483d7b,0x3d7f3bc9,0x3d35bd35,0xbd46bd22,0xbd0e3d55,0x3d623cf1,0x3d6dbcc4,0xbcf1bd62,0xbd553d0e,0x3d223d46,0x3d800000,0xbbc9bd7f,0xbd7b3c48,0x3c953d75,
0x3d6d3cc4,0x3c95bd75,0xbd7bbc48,0xbbc93d7f,0x3d353d35,0x3d22bd46,0xbd55bd0e,0xbcf13d62,0x3cc43d6d,0x3d62bcf1,0xbd0ebd55,0xbd463d22,0x3d80,0x3d7fbbc9,0xbc48bd7b,0xbd753c95,
0xbd800000,0x3d7f3bc9,0xbd7bbc48,0x3d753c95,0xbd6dbcc4,0x3d623cf1,0xbd55bd0e,0x3d463d22,0xbd35bd35,0x3d223d46,0xbd0ebd55,0x3cf13d62,0xbcc4bd6d,0x3c953d75,0xbc48bd7b,0x3bc93d7f,
0x8000bd80,0xbbc93d7f,0x3c48bd7b,0xbc953d75,0x3cc4bd6d,0xbcf13d62,0x3d0ebd55,0xbd223d46,0x3d35bd35,0xbd463d22,0x3d55bd0e,0xbd623cf1,0x3d6dbcc4,0xbd753c95,0x3d7bbc48,0xbd7f3bc9,
0xbcc4bd6d,0x3bc93d7f,0x3c48bd7b,0xbcf13d62,0xbd800000,0x3d753c95,0xbd55bd0e,0x3d223d46,0x3d6d3cc4,0xbd46bd22,0x3d0e3d55,0xbc95bd75,0x3d35bd35,0xbd623cf1,0x3d7bbc48,0xbd7fbbc9,
0xbd6d3cc4,0x3d7fbbc9,0xbd7bbc48,0x3d623cf1,0x80003d80,0x3c95bd75,0xbd0e3d55,0x3d46bd22,0x3cc4bd6d,0xbd223d46,0x3d55bd0e,0xbd753c95,0xbd35bd35,0x3cf13d62,0xbc48bd7b,0xbbc93d7f,
0x3d353d35,0xbc95bd75,0xbc483d7b,0x3d22bd46,0xbd6d3cc4,0x3d7f3bc9,0xbd55bd0e,0x3cf13d62,0xbd800000,0x3d623cf1,0xbd0ebd55,0x3bc93d7f,0x3cc4bd6d,0xbd463d22,0x3d7bbc48,0xbd75bc95,
0xbd353d35,0x3d75bc95,0xbd7bbc48,0x3d463d22,0xbcc4bd6d,0xbbc93d7f,0x3d0ebd55,0xbd623cf1,0x8000bd80,0xbcf13d62,0x3d55bd0e,0xbd7f3bc9,0x3d6d3cc4,0xbd22bd46,0x3c483d7b,0x3c95bd75,
0x3cc4bd6d,0xbd623cf1,0x3d7b3c48,0xbd22bd46,0xbd353d35,0x3d7fbbc9,0xbd55bd0e,0x3c953d75,0x3d6dbcc4,0xbd75bc95,0x3d0e3d55,0x3bc9bd7f,0xbd800000,0x3d463d22,0xbc48bd7b,0xbcf13d62,
0xbd6dbcc4,0x3cf13d62,0x3c48bd7b,0xbd463d22,0x3d353d35,0xbbc9bd7f,0xbd0e3d55,0x3d75bc95,0xbcc4bd6d,0xbc953d75,0x3d55bd0e,0xbd7fbbc9,0x80003d80,0x3d22bd46,0xbd7b3c48,0x3d623cf1,
0x8000bd80,0xbd463d22,0x3d7b3c48,0xbcf1bd62,0xbcc43d6d,0x3d75bc95,0xbd55bd0e,0x3bc93d7f,0x3d35bd35,0xbd7fbbc9,0x3d0e3d55,0x3c95bd75,0xbd6d3cc4,0x3d623cf1,0xbc48bd7b,0xbd223d46,
0xbd800000,0x3d223d46,0x3c48bd7b,0xbd623cf1,0x3d6d3cc4,0xbc95bd75,0xbd0e3d55,0x3d7fbbc9,0xbd35bd35,0xbbc93d7f,0x3d55bd0e,0xbd75bc95,0x3cc43d6d,0x3cf1bd62,0xbd7b3c48,0x3d463d22,
0x3d6dbcc4,0xbd46bd22,0xbc483d7b,0x3d75bc95,0x80003d80,0x3d62bcf1,0xbd55bd0e,0xbbc93d7f,0xbcc43d6d,0x3d7fbbc9,0xbd0ebd55,0xbcf13d62,0xbd35bd35,0xbc953d75,0x3d7bbc48,0xbd22bd46,
0x3cc43d6d,0x3d22bd46,0xbd7bbc48,0x3c953d75,0xbd800000,0x3cf13d62,0x3d0ebd55,0xbd7fbbc9,0xbd6dbcc4,0x3bc93d7f,0x3d55bd0e,0xbd62bcf1,0x3d35bd35,0xbd75bc95,0x3c483d7b,0x3d46bd22,
0xbd353d35,0x3d623cf1,0x3c48bd7b,0xbd7f3bc9,0x3cc43d6d,0x3d46bd22,0xbd55bd0e,0xbc953d75,0x8000bd80,0xbd753c95,0x3d0e3d55,0x3d22bd46,0xbd6dbcc4,0xbbc93d7f,0x3d7bbc48,0xbcf1bd62,
0x3d353d35,0x3cf1bd62,0xbd7bbc48,0x3bc93d7f,0x3d6dbcc4,0xbd22bd46,0xbd0e3d55,0x3d753c95,0xbd800000,0x3c953d75,0x3d55bd0e,0xbd46bd22,0xbcc43d6d,0x3d7f3bc9,0xbc48bd7b,0xbd623cf1,
0x3d6d3cc4,0x3c95bd75,0xbd7bbc48,0xbbc93d7f,0x3d353d35,0x3d22bd46,0xbd55bd0e,0xbcf13d62,0x3cc43d6d,0x3d62bcf1,0xbd0ebd55,0xbd463d22,0x80003d80,0x3d7fbbc9,0xbc48bd7b,0xbd753c95,
0xbcc43d6d,0x3d753c95,0x3c48bd7b,0xbd7fbbc9,0xbd353d35,0x3d463d22,0x3d0ebd55,0xbd62bcf1,0xbd6d3cc4,0x3cf13d62,0x3d55bd0e,0xbd22bd46,0xbd800000,0x3bc93d7f,0x3d7bbc48,0xbc95bd75,
0x3d80,0x3d7f3bc9,0x3c48bd7b,0xbd75bc95,0xbcc43d6d,0x3d623cf1,0x3d0ebd55,0xbd46bd22,0xbd353d35,0x3d223d46,0x3d55bd0e,0xbcf1bd62,0xbd6d3cc4,0x3c953d75,0x3d7bbc48,0xbbc9bd7f,
0xbd800000,0xbbc93d7f,0x3d7b3c48,0x3c95bd75,0xbd6dbcc4,0xbcf13d62,0x3d553d0e,0x3d22bd46,0xbd35bd35,0xbd463d22,0x3d0e3d55,0x3d62bcf1,0xbcc4bd6d,0xbd753c95,0x3c483d7b,0x3d7fbbc9,
0xbd6d3cc4,0x3bc93d7f,0x3d7b3c48,0x3cf1bd62,0x3d80,0x3d753c95,0x3d0ebd55,0xbd22bd46,0x3cc4bd6d,0xbd46bd22,0xbd553d0e,0x3c953d75,0xbd35bd35,0xbd623cf1,0x3c483d7b,0x3d7f3bc9,
0x3cc43d6d,0x3d7fbbc9,0x3c48bd7b,0xbd62bcf1,0x3d800000,0x3c95bd75,0xbd55bd0e,0xbd463d22,0xbd6dbcc4,0xbd223d46,0x3d0e3d55,0x3d75bc95,0xbd353d35,0x3cf13d62,0x3d7bbc48,0x3bc9bd7f,
0x3d35bd35,0xbc95bd75,0xbd7bbc48,0xbd223d46,0x3cc43d6d,0x3d7f3bc9,0x3d0ebd55,0xbcf1bd62,0x3d80,0x3d623cf1,0x3d55bd0e,0xbbc9bd7f,0xbd6dbcc4,0xbd463d22,0x3c483d7b,0x3d753c95,
0x3d353d35,0x3d75bc95,0x3c48bd7b,0xbd46bd22,0xbd6d3cc4,0xbbc93d7f,0x3d553d0e,0x3d62bcf1,0xbd800000,0xbcf13d62,0x3d0e3d55,0x3d7fbbc9,0x3cc4bd6d,0xbd22bd46,0xbd7b3c48,0xbc953d75,
0xbd6dbcc4,0xbd623cf1,0xbc483d7b,0x3d223d46,0x3d353d35,0x3d7fbbc9,0x3d0ebd55,0xbc95bd75,0xbcc4bd6d,0xbd75bc95,0xbd553d0e,0xbbc93d7f,0x3d80,0x3d463d22,0x3d7bbc48,0x3cf1bd62,
0xbcc43d6d,0x3cf13d62,0x3d7b3c48,0x3d46bd22,0x3d35bd35,0xbbc9bd7f,0xbd55bd0e,0xbd753c95,0xbd6d3cc4,0xbc953d75,0x3d0e3d55,0x3d7f3bc9,0x3d800000,0x3d22bd46,0xbc48bd7b,0xbd62bcf1,
0xbd800000,0xbd463d22,0xbc483d7b,0x3cf13d62,0x3d6d3cc4,0x3d75bc95,0x3d0ebd55,0xbbc9bd7f,0xbd35bd35,0xbd7fbbc9,0xbd553d0e,0xbc953d75,0x3cc43d6d,0x3d623cf1,0x3d7bbc48,0x3d22bd46,
0x3d80,0x3d223d46,0x3d7b3c48,0x3d62bcf1,0x3cc4bd6d,0xbc95bd75,0xbd55bd0e,0xbd7f3bc9,0xbd353d35,0xbbc93d7f,0x3d0e3d55,0x3d753c95,0x3d6dbcc4,0x3cf1bd62,0xbc48bd7b,0xbd46bd22,
0xbcc4bd6d,0xbd46bd22,0xbd7bbc48,0xbd753c95,0x3d800000,0x3d62bcf1,0x3d0ebd55,0x3bc9bd7f,0x3d6d3cc4,0x3d7fbbc9,0x3d55bd0e,0x3cf1bd62,0xbd353d35,0xbc953d75,0x3c483d7b,0x3d223d46,
0x3d6dbcc4,0x3d22bd46,0x3c48bd7b,0xbc95bd75,0x3d80,0x3cf13d62,0x3d553d0e,0x3d7f3bc9,0xbcc43d6d,0x3bc93d7f,0x3d0e3d55,0x3d623cf1,0xbd35bd35,0xbd75bc95,0xbd7b3c48,0xbd463d22,
0x3d353d35,0x3d623cf1,0x3d7b3c48,0x3d7fbbc9,0x3d6dbcc4,0x3d46bd22,0x3d0ebd55,0x3c95bd75,0xbd800000,0xbd753c95,0xbd553d0e,0xbd223d46,0xbcc43d6d,0xbbc93d7f,0x3c483d7b,0x3cf13d62,
0x3d35bd35,0x3cf1bd62,0x3c48bd7b,0xbbc9bd7f,0xbcc4bd6d,0xbd22bd46,0xbd55bd0e,0xbd75bc95,0x3d80,0x3c953d75,0x3d0e3d55,0x3d463d22,0x3d6d3cc4,0x3d7f3bc9,0x3d7bbc48,0x3d62bcf1,
0x3cc4bd6d,0x3c95bd75,0x3c48bd7b,0x3bc9bd7f,0x3d35bd35,0x3d22bd46,0x3d0ebd55,0x3cf1bd62,0x3d6dbcc4,0x3d62bcf1,0x3d55bd0e,0x3d46bd22,0x3d800000,0x3d7fbbc9,0x3d7bbc48,0x3d75bc95,
0x3d6d3cc4,0x3d753c95,0x3d7b3c48,0x3d7f3bc9,0x3d353d35,0x3d463d22,0x3d553d0e,0x3d623cf1,0x3cc43d6d,0x3cf13d62,0x3d0e3d55,0x3d223d46,0x3d80,0x3bc93d7f,0x3c483d7b,0x3c953d75,
0xbd800000,0xbbc93d7f,0x3d7b3c48,0x3c95bd75,0xbd6dbcc4,0xbcf13d62,0x3d553d0e,0x3d22bd46,0xbd35bd35,0xbd463d22,0x3d0e3d55,0x3d62bcf1,0xbcc4bd6d,0xbd753c95,0x3c483d7b,0x3d7fbbc9,
0x8000bd80,0xbd7fbbc9,0xbc483d7b,0x3d753c95,0x3cc4bd6d,0xbd62bcf1,0xbd0e3d55,0x3d463d22,0x3d35bd35,0xbd22bd46,0xbd553d0e,0x3cf13d62,0x3d6dbcc4,0xbc95bd75,0xbd7b3c48,0x3bc93d7f,
0xbcc4bd6d,0xbd7f3bc9,0xbc483d7b,0x3d623cf1,0xbd800000,0xbc953d75,0x3d553d0e,0x3d46bd22,0x3d6d3cc4,0x3d22bd46,0xbd0ebd55,0xbd753c95,0x3d35bd35,0xbcf1bd62,0xbd7b3c48,0xbbc93d7f,
0xbd6d3cc4,0x3bc93d7f,0x3d7b3c48,0x3cf1bd62,0x80003d80,0x3d753c95,0x3d0ebd55,0xbd22bd46,0x3cc4bd6d,0xbd46bd22,0xbd553d0e,0x3c953d75,0xbd35bd35,0xbd623cf1,0x3c483d7b,0x3d7f3bc9,
0x3d353d35,0x3d75bc95,0x3c48bd7b,0xbd46bd22,0xbd6d3cc4,0xbbc93d7f,0x3d553d0e,0x3d62bcf1,0xbd800000,0xbcf13d62,0x3d0e3d55,0x3d7fbbc9,0x3cc4bd6d,0xbd22bd46,0xbd7b3c48,0xbc953d75,
0xbd353d35,0x3c953d75,0x3d7b3c48,0x3d22bd46,0xbcc4bd6d,0xbd7fbbc9,0xbd0e3d55,0x3cf13d62,0x8000bd80,0xbd62bcf1,0xbd553d0e,0x3bc93d7f,0x3d6d3cc4,0x3d46bd22,0xbc48bd7b,0xbd75bc95,
0x3cc4bd6d,0xbcf1bd62,0xbd7bbc48,0xbd463d22,0xbd353d35,0x3bc93d7f,0x3d553d0e,0x3d75bc95,0x3d6dbcc4,0x3c95bd75,0xbd0ebd55,0xbd7fbbc9,0xbd800000,0xbd223d46,0x3c483d7b,0x3d623cf1,
0xbd6dbcc4,0xbd623cf1,0xbc483d7b,0x3d223d46,0x3d353d35,0x3d7fbbc9,0x3d0ebd55,0xbc95bd75,0xbcc4bd6d,0xbd75bc95,0xbd553d0e,0xbbc93d7f,0x80003d80,0x3d463d22,0x3d7bbc48,0x3cf1bd62,
0x8000bd80,0xbd22bd46,0xbd7bbc48,0xbd623cf1,0xbcc43d6d,0x3c953d75,0x3d553d0e,0x3d7fbbc9,0x3d35bd35,0x3bc9bd7f,0xbd0ebd55,0xbd75bc95,0xbd6d3cc4,0xbcf13d62,0x3c483d7b,0x3d463d22,
0xbd800000,0xbd463d22,0xbc483d7b,0x3cf13d62,0x3d6d3cc4,0x3d75bc95,0x3d0ebd55,0xbbc9bd7f,0xbd35bd35,0xbd7fbbc9,0xbd553d0e,0xbc953d75,0x3cc43d6d,0x3d623cf1,0x3d7bbc48,0x3d22bd46,
0x3d6dbcc4,0x3d22bd46,0x3c48bd7b,0xbc95bd75,0x80003d80,0x3cf13d62,0x3d553d0e,0x3d7f3bc9,0xbcc43d6d,0x3bc93d7f,0x3d0e3d55,0x3d623cf1,0xbd35bd35,0xbd75bc95,0xbd7b3c48,0xbd463d22,
0x3cc43d6d,0x3d463d22,0x3d7b3c48,0x3d75bc95,0xbd800000,0xbd623cf1,0xbd0e3d55,0xbbc93d7f,0xbd6dbcc4,0xbd7f3bc9,0xbd553d0e,0xbcf13d62,0x3d35bd35,0x3c95bd75,0xbc48bd7b,0xbd22bd46,
0xbd353d35,0xbcf13d62,0xbc483d7b,0x3bc93d7f,0x3cc43d6d,0x3d223d46,0x3d553d0e,0x3d753c95,0x8000bd80,0xbc95bd75,0xbd0ebd55,0xbd46bd22,0xbd6dbcc4,0xbd7fbbc9,0xbd7b3c48,0xbd623cf1,
0x3d353d35,0x3d623cf1,0x3d7b3c48,0x3d7fbbc9,0x3d6dbcc4,0x3d46bd22,0x3d0ebd55,0x3c95bd75,0xbd800000,0xbd753c95,0xbd553d0e,0xbd223d46,0xbcc43d6d,0xbbc93d7f,0x3c483d7b,0x3cf13d62,
0x3d6d3cc4,0x3d753c95,0x3d7b3c48,0x3d7f3bc9,0x3d353d35,0x3d463d22,0x3d553d0e,0x3d623cf1,0x3cc43d6d,0x3cf13d62,0x3d0e3d55,0x3d223d46,0x80003d80,0x3bc93d7f,0x3c483d7b,0x3c953d75,
0xbcc43d6d,0xbc953d75,0xbc483d7b,0xbbc93d7f,0xbd353d35,0xbd223d46,0xbd0e3d55,0xbcf13d62,0xbd6d3cc4,0xbd623cf1,0xbd553d0e,0xbd463d22,0xbd800000,0xbd7f3bc9,0xbd7b3c48,0xbd753c95,
0x3d80,0xbc163d7d,0xbc953d75,0xbcdb3d67,0xbd0e3d55,0xbd2c3d3e,0xbd463d22,0xbd5c3d04,0xbd6d3cc4,0xbd783c79,0xbd7f3bc9,0xbd80bb49,0xbd7bbc48,0xbd71bcac,0xbd62bcf1,0xbd4ebd18,
0xbd35bd35,0xbd18bd4e,0xbcf1bd62,0xbcacbd71,0xbc48bd7b,0xbb49bd80,0x3bc9bd7f,0x3c79bd78,0x3cc4bd6d,0x3d04bd5c,0x3d22bd46,0x3d3ebd2c,0x3d55bd0e,0x3d67bcdb,0x3d75bc95,0x3d7dbc16,
0xbd7b3c48,0xbd7dbc16,0xbd62bcf1,0xbd2cbd3e,0x3d80,0xbcac3d71,0xbd223d46,0xbd5c3d04,0x3d55bd0e,0x3d78bc79,0x3d7f3bc9,0x3d673cdb,0xbcc4bd6d,0xbb49bd80,0x3c95bd75,0x3d18bd4e,
0xbd0e3d55,0xbd4e3d18,0xbd753c95,0xbd80bb49,0x3d353d35,0x3cdb3d67,0x3bc93d7f,0xbc793d78,0x3c48bd7b,0x3d04bd5c,0x3d46bd22,0x3d71bcac,0xbd6dbcc4,0xbd3ebd2c,0xbcf1bd62,0xbc16bd7d,
0x3d6dbcc4,0x3d7d3c16,0x3d463d22,0x3cac3d71,0xbc483d7b,0xbd2c3d3e,0xbd753c95,0xbd78bc79,0x3d80,0xbd043d5c,0xbd623cf1,0xbd80bb49,0xbd55bd0e,0xbcdbbd67,0x3bc9bd7f,0x3d18bd4e,
0xbcc43d6d,0xbd4e3d18,0xbd7f3bc9,0xbd67bcdb,0xbd0ebd55,0xbb49bd80,0x3cf1bd62,0x3d5cbd04,0xbd35bd35,0xbc79bd78,0x3c95bd75,0x3d3ebd2c,0x3d7bbc48,0x3d713cac,0x3d223d46,0x3c163d7d,
0xbd0ebd55,0x3c16bd7d,0x3d46bd22,0x3d803b49,0x3cc43d6d,0xbcac3d71,0xbd623cf1,0xbd78bc79,0xbc48bd7b,0x3d04bd5c,0x3d75bc95,0x3d673cdb,0x3d80,0xbd2c3d3e,0xbd7f3bc9,0xbd4ebd18,
0xbd7bbc48,0xbd18bd4e,0x3bc9bd7f,0x3d3ebd2c,0x3d6d3cc4,0x3cdb3d67,0xbc953d75,0xbd5c3d04,0xbd55bd0e,0xbc79bd78,0x3cf1bd62,0x3d71bcac,0x3d353d35,0x3b493d80,0xbd223d46,0xbd7d3c16,
0xbd35bd35,0x3c16bd7d,0x3d62bcf1,0x3d673cdb,0x3c483d7b,0xbd2c3d3e,0xbd7fbbc9,0xbd04bd5c,0x3cc4bd6d,0x3d78bc79,0x3d463d22,0xbb493d80,0xbd553d0e,0xbd71bcac,0xbc95bd75,0x3d18bd4e,
0x3d80,0xbd4e3d18,0xbd75bc95,0xbcacbd71,0x3d0ebd55,0x3d80bb49,0x3d223d46,0xbc793d78,0xbd6d3cc4,0xbd5cbd04,0xbbc9bd7f,0x3d3ebd2c,0x3d7b3c48,0x3cdb3d67,0xbcf13d62,0xbd7d3c16,
0x3d0ebd55,0x3d7d3c16,0x3c953d75,0xbd3e3d2c,0x3d353d35,0xbcac3d71,0xbd7f3bc9,0xbd04bd5c,0xbc483d7b,0xbd783c79,0xbd22bd46,0x3cdbbd67,0xbd6dbcc4,0xbb49bd80,0x3d62bcf1,0x3d4e3d18,
0x3d7bbc48,0x3d183d4e,0xbcf13d62,0xbd80bb49,0x3d80,0xbd673cdb,0xbd46bd22,0x3c79bd78,0xbd553d0e,0xbd5cbd04,0x3bc9bd7f,0x3d71bcac,0xbcc4bd6d,0x3d2cbd3e,0x3d753c95,0x3c163d7d,
0xbcc43d6d,0xbd7dbc16,0xbbc9bd7f,0x3d71bcac,0x3d0e3d55,0xbd2c3d3e,0xbd62bcf1,0x3c79bd78,0xbd35bd35,0x3d04bd5c,0x3d753c95,0xbb493d80,0xbd7b3c48,0xbcdbbd67,0x3d46bd22,0x3d4e3d18,
0x3d6dbcc4,0x3d183d4e,0xbd223d46,0xbd67bcdb,0x3c48bd7b,0x3d80bb49,0x3c953d75,0xbd5c3d04,0x3d80,0xbd783c79,0xbcf1bd62,0x3d3ebd2c,0x3d553d0e,0xbcac3d71,0xbd7fbbc9,0xbc16bd7d,
0x3d7b3c48,0xbc163d7d,0xbd7fbbc9,0x3b49bd80,0x3d6d3cc4,0xbcac3d71,0xbd75bc95,0x3c79bd78,0x3d553d0e,0xbd043d5c,0xbd62bcf1,0x3cdbbd67,0x3d353d35,0xbd2c3d3e,0xbd46bd22,0x3d18bd4e,
0x3d0e3d55,0xbd4e3d18,0xbd22bd46,0x3d3ebd2c,0x3cc43d6d,0xbd673cdb,0xbcf1bd62,0x3d5cbd04,0x3c483d7b,0xbd783c79,0xbc95bd75,0x3d71bcac,0x3d80,0xbd803b49,0xbbc9bd7f,0x3d7dbc16,
0xbd800000,0xbd7dbc16,0xbd75bc95,0xbd67bcdb,0xbd55bd0e,0xbd3ebd2c,0xbd22bd46,0xbd04bd5c,0xbcc4bd6d,0xbc79bd78,0xbbc9bd7f,0x3b49bd80,0x3c48bd7b,0x3cacbd71,0x3cf1bd62,0x3d18bd4e,
0x3d35bd35,0x3d4ebd18,0x3d62bcf1,0x3d71bcac,0x3d7bbc48,0x3d80bb49,0x3d7f3bc9,0x3d783c79,0x3d6d3cc4,0x3d5c3d04,0x3d463d22,0x3d2c3d3e,0x3d0e3d55,0x3cdb3d67,0x3c953d75,0x3c163d7d,
0xbc48bd7b,0x3c16bd7d,0x3cf1bd62,0x3d3ebd2c,0xbd800000,0xbd71bcac,0xbd46bd22,0xbd04bd5c,0x3d0e3d55,0x3c793d78,0xbbc93d7f,0xbcdb3d67,0x3d6dbcc4,0x3d80bb49,0x3d753c95,0x3d4e3d18,
0xbd55bd0e,0xbd18bd4e,0xbc95bd75,0x3b49bd80,0xbd353d35,0xbd673cdb,0xbd7f3bc9,0xbd78bc79,0x3d7b3c48,0x3d5c3d04,0x3d223d46,0x3cac3d71,0x3cc4bd6d,0x3d2cbd3e,0x3d62bcf1,0x3d7dbc16,
0x3cc43d6d,0xbc163d7d,0xbd223d46,0xbd713cac,0xbd7bbc48,0xbd3ebd2c,0xbc95bd75,0x3c79bd78,0xbd800000,0xbd5cbd04,0xbcf1bd62,0x3b49bd80,0x3d0ebd55,0x3d67bcdb,0x3d7f3bc9,0x3d4e3d18,
0xbd6dbcc4,0xbd18bd4e,0xbbc9bd7f,0x3cdbbd67,0x3d55bd0e,0x3d80bb49,0x3d623cf1,0x3d043d5c,0x3d35bd35,0x3d78bc79,0x3d753c95,0x3d2c3d3e,0x3c483d7b,0xbcac3d71,0xbd463d22,0xbd7d3c16,
0x3d55bd0e,0x3d7d3c16,0x3d223d46,0xbb493d80,0xbd6d3cc4,0xbd71bcac,0xbcf1bd62,0x3c79bd78,0x3d7bbc48,0x3d5c3d04,0x3c953d75,0xbcdb3d67,0xbd800000,0xbd3ebd2c,0xbbc9bd7f,0x3d18bd4e,
0x3c48bd7b,0x3d4ebd18,0x3d7f3bc9,0x3d2c3d3e,0xbcc43d6d,0xbd673cdb,0xbd75bc95,0xbd04bd5c,0x3d0ebd55,0x3d78bc79,0x3d623cf1,0x3cac3d71,0xbd353d35,0xbd803b49,0xbd46bd22,0xbc16bd7d,
0x3d35bd35,0x3d7d3c16,0x3cf13d62,0xbcdb3d67,0xbd7b3c48,0xbd3ebd2c,0x3bc9bd7f,0x3d5cbd04,0x3d6d3cc4,0x3c793d78,0xbd223d46,0xbd80bb49,0xbd0ebd55,0x3cacbd71,0x3d75bc95,0x3d4e3d18,
0xbd800000,0xbd18bd4e,0x3c95bd75,0x3d71bcac,0x3d553d0e,0x3b493d80,0xbd463d22,0xbd78bc79,0xbcc4bd6d,0x3d04bd5c,0x3d7fbbc9,0x3d2c3d3e,0xbc483d7b,0xbd673cdb,0xbd62bcf1,0xbc16bd7d,
0x3d553d0e,0xbc163d7d,0xbd753c95,0xbd2cbd3e,0xbd353d35,0xbd71bcac,0xbbc9bd7f,0x3d5cbd04,0xbd7bbc48,0xbc79bd78,0x3d46bd22,0x3d673cdb,0x3cc4bd6d,0x3d80bb49,0x3cf13d62,0xbd183d4e,
0x3c483d7b,0xbd4e3d18,0xbd62bcf1,0x3b49bd80,0xbd800000,0xbcdbbd67,0x3d22bd46,0x3d783c79,0xbd0ebd55,0x3d04bd5c,0x3d7f3bc9,0x3cac3d71,0x3d6dbcc4,0x3d3e3d2c,0xbc953d75,0xbd7d3c16,
0xbd6dbcc4,0x3c16bd7d,0x3d7fbbc9,0x3cac3d71,0xbd553d0e,0xbd3ebd2c,0x3cf1bd62,0x3d783c79,0x3d35bd35,0x3d5c3d04,0xbc953d75,0xbd80bb49,0xbc48bd7b,0x3d67bcdb,0x3d223d46,0xbd183d4e,
0x3cc43d6d,0xbd4e3d18,0xbd46bd22,0x3cdbbd67,0x3d7b3c48,0x3b493d80,0xbd753c95,0xbd04bd5c,0xbd800000,0xbc79bd78,0x3d62bcf1,0x3d2c3d3e,0xbd0e3d55,0xbd71bcac,0x3bc9bd7f,0x3d7dbc16,
0xbc483d7b,0xbd7dbc16,0x3bc9bd7f,0x3d803b49,0xbcc43d6d,0xbd71bcac,0x3c95bd75,0x3d783c79,0xbd0e3d55,0xbd5cbd04,0x3cf1bd62,0x3d673cdb,0xbd353d35,0xbd3ebd2c,0x3d22bd46,0x3d4e3d18,
0xbd553d0e,0xbd18bd4e,0x3d46bd22,0x3d2c3d3e,0xbd6d3cc4,0xbcdbbd67,0x3d62bcf1,0x3d043d5c,0xbd7b3c48,0xbc79bd78,0x3d75bc95,0x3cac3d71,0xbd800000,0xbb49bd80,0x3d7fbbc9,0x3c163d7d,
0x3d80,0xbd7dbc16,0x3c95bd75,0x3d673cdb,0xbd0e3d55,0xbd3ebd2c,0x3d46bd22,0x3d043d5c,0xbd6d3cc4,0xbc79bd78,0x3d7fbbc9,0xbb493d80,0xbd7bbc48,0x3cacbd71,0x3d623cf1,0xbd183d4e,
0xbd35bd35,0x3d4ebd18,0x3cf13d62,0xbd713cac,0xbc48bd7b,0x3d80bb49,0xbbc93d7f,0xbd78bc79,0x3cc4bd6d,0x3d5c3d04,0xbd223d46,0xbd2cbd3e,0x3d55bd0e,0x3cdb3d67,0xbd753c95,0xbc16bd7d,
0xbd7b3c48,0x3c16bd7d,0x3d623cf1,0xbd3e3d2c,0x3d80,0xbd71bcac,0x3d22bd46,0x3d043d5c,0x3d55bd0e,0x3c793d78,0xbd7fbbc9,0x3cdbbd67,0xbcc4bd6d,0x3d80bb49,0xbc953d75,0xbd4ebd18,
0xbd0e3d55,0xbd18bd4e,0x3d75bc95,0xbb493d80,0x3d353d35,0xbd673cdb,0xbbc9bd7f,0x3d783c79,0x3c48bd7b,0x3d5c3d04,0xbd463d22,0xbcacbd71,0xbd6dbcc4,0x3d2cbd3e,0x3cf13d62,0xbd7d3c16,
0x3d6dbcc4,0xbc163d7d,0xbd46bd22,0x3d71bcac,0xbc483d7b,0xbd3ebd2c,0x3d75bc95,0xbc793d78,0x3d80,0xbd5cbd04,0x3d62bcf1,0xbb493d80,0xbd55bd0e,0x3d67bcdb,0xbbc93d7f,0xbd4ebd18,
0xbcc43d6d,0xbd18bd4e,0x3d7fbbc9,0xbcdb3d67,0xbd0ebd55,0x3d80bb49,0xbcf13d62,0xbd04bd5c,0xbd35bd35,0x3d78bc79,0xbc953d75,0xbd2cbd3e,0x3d7bbc48,0xbcac3d71,0xbd22bd46,0x3d7dbc16,
0xbd0ebd55,0x3d7d3c16,0xbd463d22,0x3b49bd80,0x3cc43d6d,0xbd71bcac,0x3d62bcf1,0xbc793d78,0xbc48bd7b,0x3d5c3d04,0xbd753c95,0x3cdbbd67,0x3d80,0xbd3ebd2c,0x3d7fbbc9,0xbd183d4e,
0xbd7bbc48,0x3d4ebd18,0xbbc93d7f,0xbd2cbd3e,0x3d6d3cc4,0xbd673cdb,0x3c95bd75,0x3d043d5c,0xbd55bd0e,0x3d78bc79,0xbcf13d62,0xbcacbd71,0x3d353d35,0xbd803b49,0x3d22bd46,0x3c163d7d,
0xbd35bd35,0x3d7d3c16,0xbd623cf1,0x3cdbbd67,0x3c483d7b,0xbd3ebd2c,0x3d7f3bc9,0xbd5c3d04,0x3cc4bd6d,0x3c793d78,0xbd46bd22,0x3d803b49,0xbd553d0e,0x3cacbd71,0x3c953d75,0xbd4ebd18,
0x3d80,0xbd18bd4e,0x3d753c95,0xbd713cac,0x3d0ebd55,0x3b493d80,0xbd22bd46,0x3d783c79,0xbd6d3cc4,0x3d04bd5c,0x3bc93d7f,0xbd2cbd3e,0x3d7b3c48,0xbd673cdb,0x3cf1bd62,0x3c163d7d,
0x3d0ebd55,0xbc163d7d,0xbc95bd75,0x3d2c3d3e,0x3d353d35,0xbd71bcac,0x3d7fbbc9,0xbd5c3d04,0xbc483d7b,0xbc79bd78,0x3d223d46,0xbd67bcdb,0xbd6dbcc4,0x3d80bb49,0xbd623cf1,0x3d18bd4e,
0x3d7bbc48,0xbd4e3d18,0x3cf1bd62,0xbb493d80,0x3d80,0xbcdbbd67,0x3d463d22,0xbd78bc79,0xbd553d0e,0x3d04bd5c,0xbbc93d7f,0xbcacbd71,0xbcc4bd6d,0x3d3e3d2c,0xbd75bc95,0x3d7dbc16,
0xbcc43d6d,0x3c16bd7d,0x3bc93d7f,0xbcacbd71,0x3d0e3d55,0xbd3ebd2c,0x3d623cf1,0xbd78bc79,0xbd35bd35,0x3d5c3d04,0xbd75bc95,0x3d803b49,0xbd7b3c48,0x3d67bcdb,0xbd463d22,0x3d18bd4e,
0x3d6dbcc4,0xbd4e3d18,0x3d22bd46,0xbcdb3d67,0x3c48bd7b,0x3b493d80,0xbc95bd75,0x3d043d5c,0x3d80,0xbc79bd78,0x3cf13d62,0xbd2cbd3e,0x3d553d0e,0xbd71bcac,0x3d7f3bc9,0xbd7d3c16,
0x3d7b3c48,0xbd7dbc16,0x3d7f3bc9,0xbd80bb49,0x3d6d3cc4,0xbd71bcac,0x3d753c95,0xbd78bc79,0x3d553d0e,0xbd5cbd04,0x3d623cf1,0xbd67bcdb,0x3d353d35,0xbd3ebd2c,0x3d463d22,0xbd4ebd18,
0x3d0e3d55,0xbd18bd4e,0x3d223d46,0xbd2cbd3e,0x3cc43d6d,0xbcdbbd67,0x3cf13d62,0xbd04bd5c,0x3c483d7b,0xbc79bd78,0x3c953d75,0xbcacbd71,0x3d80,0xbb49bd80,0x3bc93d7f,0xbc16bd7d,
0xbd800000,0x3c16bd7d,0x3d753c95,0xbcdb3d67,0xbd55bd0e,0x3d2cbd3e,0x3d223d46,0xbd5c3d04,0xbcc4bd6d,0x3d78bc79,0x3bc93d7f,0xbd80bb49,0x3c48bd7b,0x3d713cac,0xbcf13d62,0xbd4ebd18,
0x3d35bd35,0x3d183d4e,0xbd623cf1,0xbcacbd71,0x3d7bbc48,0x3b493d80,0xbd7fbbc9,0x3c79bd78,0x3d6d3cc4,0xbd043d5c,0xbd46bd22,0x3d3ebd2c,0x3d0e3d55,0xbd673cdb,0xbc95bd75,0x3d7dbc16,
0xbc48bd7b,0x3d7d3c16,0xbcf13d62,0xbd2cbd3e,0xbd800000,0x3cacbd71,0x3d463d22,0xbd5c3d04,0x3d0e3d55,0xbd783c79,0x3bc9bd7f,0x3d673cdb,0x3d6dbcc4,0x3b493d80,0xbd75bc95,0x3d18bd4e,
0xbd55bd0e,0x3d4ebd18,0x3c953d75,0xbd80bb49,0xbd353d35,0xbcdbbd67,0x3d7fbbc9,0xbc793d78,0x3d7b3c48,0xbd043d5c,0xbd22bd46,0x3d71bcac,0x3cc4bd6d,0x3d3e3d2c,0xbd623cf1,0xbc16bd7d,
0x3cc43d6d,0xbd7dbc16,0x3d22bd46,0x3cac3d71,0xbd7bbc48,0x3d2cbd3e,0x3c953d75,0xbd78bc79,0xbd800000,0x3d04bd5c,0x3cf13d62,0xbd80bb49,0x3d0ebd55,0x3cdb3d67,0xbd7fbbc9,0x3d18bd4e,
0xbd6dbcc4,0x3d4ebd18,0x3bc93d7f,0xbd67bcdb,0x3d55bd0e,0x3b493d80,0xbd62bcf1,0x3d5cbd04,0x3d35bd35,0x3c793d78,0xbd75bc95,0x3d3ebd2c,0x3c483d7b,0xbd71bcac,0x3d46bd22,0x3c163d7d,
0x3d55bd0e,0xbc163d7d,0xbd22bd46,0x3d803b49,0xbd6d3cc4,0x3cacbd71,0x3cf13d62,0xbd78bc79,0x3d7bbc48,0xbd043d5c,0xbc95bd75,0x3d673cdb,0xbd800000,0x3d2cbd3e,0x3bc93d7f,0xbd4ebd18,
0x3c48bd7b,0x3d183d4e,0xbd7fbbc9,0x3d3ebd2c,0xbcc43d6d,0xbcdbbd67,0x3d753c95,0xbd5c3d04,0x3d0ebd55,0x3c793d78,0xbd62bcf1,0x3d71bcac,0xbd353d35,0xbb49bd80,0x3d463d22,0xbd7d3c16,
0x3d35bd35,0xbc163d7d,0xbcf1bd62,0x3d673cdb,0xbd7b3c48,0x3d2cbd3e,0xbbc93d7f,0xbd04bd5c,0x3d6d3cc4,0xbd783c79,0x3d22bd46,0xbb493d80,0xbd0ebd55,0x3d713cac,0xbd753c95,0x3d18bd4e,
0xbd800000,0x3d4ebd18,0xbc953d75,0xbcacbd71,0x3d553d0e,0xbd803b49,0x3d46bd22,0xbc793d78,0xbcc4bd6d,0x3d5c3d04,0xbd7f3bc9,0x3d3ebd2c,0xbc483d7b,0xbcdbbd67,0x3d623cf1,0xbd7d3c16,
0x3d553d0e,0xbd7dbc16,0x3d75bc95,0xbd3e3d2c,0xbd353d35,0x3cacbd71,0x3bc93d7f,0xbd04bd5c,0xbd7bbc48,0x3d78bc79,0xbd463d22,0x3cdbbd67,0x3cc4bd6d,0x3b493d80,0xbcf1bd62,0x3d4e3d18,
0x3c483d7b,0xbd18bd4e,0x3d623cf1,0xbd80bb49,0xbd800000,0x3d67bcdb,0xbd223d46,0x3c79bd78,0xbd0ebd55,0x3d5c3d04,0xbd7fbbc9,0x3d71bcac,0x3d6dbcc4,0xbd2c3d3e,0x3c95bd75,0x3c163d7d,
0xbd6dbcc4,0x3d7d3c16,0xbd7f3bc9,0x3d71bcac,0xbd553d0e,0x3d2cbd3e,0xbcf13d62,0x3c79bd78,0x3d35bd35,0xbd043d5c,0x3c95bd75,0xbb493d80,0xbc48bd7b,0x3cdb3d67,0xbd22bd46,0x3d4e3d18,
0x3cc43d6d,0xbd18bd4e,0x3d463d22,0xbd67bcdb,0x3d7b3c48,0xbd803b49,0x3d75bc95,0xbd5c3d04,0xbd800000,0x3d78bc79,0xbd623cf1,0x3d3ebd2c,0xbd0e3d55,0x3cacbd71,0xbbc93d7f,0xbc16bd7d,
0xbc483d7b,0x3c16bd7d,0xbbc93d7f,0x3b49bd80,0xbcc43d6d,0x3cacbd71,0xbc953d75,0x3c79bd78,0xbd0e3d55,0x3d04bd5c,0xbcf13d62,0x3cdbbd67,0xbd353d35,0x3d2cbd3e,0xbd223d46,0x3d18bd4e,
0xbd553d0e,0x3d4ebd18,0xbd463d22,0x3d3ebd2c,0xbd6d3cc4,0x3d67bcdb,0xbd623cf1,0x3d5cbd04,0xbd7b3c48,0x3d78bc79,0xbd753c95,0x3d71bcac,0xbd800000,0x3d80bb49,0xbd7f3bc9,0x3d7dbc16,
0x3d80,0x3c16bd7d,0xbc953d75,0x3cdbbd67,0xbd0e3d55,0x3d2cbd3e,0xbd463d22,0x3d5cbd04,0xbd6d3cc4,0x3d78bc79,0xbd7f3bc9,0x3d803b49,0xbd7bbc48,0x3d713cac,0xbd62bcf1,0x3d4e3d18,
0xbd35bd35,0x3d183d4e,0xbcf1bd62,0x3cac3d71,0xbc48bd7b,0x3b493d80,0x3bc9bd7f,0xbc793d78,0x3cc4bd6d,0xbd043d5c,0x3d22bd46,0xbd3e3d2c,0x3d55bd0e,0xbd673cdb,0x3d75bc95,0xbd7d3c16,
0xbd7b3c48,0x3d7d3c16,0xbd62bcf1,0x3d2c3d3e,0x3d80,0x3cacbd71,0xbd223d46,0x3d5cbd04,0x3d55bd0e,0xbd783c79,0x3d7f3bc9,0xbd67bcdb,0xbcc4bd6d,0x3b493d80,0x3c95bd75,0xbd183d4e,
0xbd0e3d55,0x3d4ebd18,0xbd753c95,0x3d803b49,0x3d353d35,0xbcdbbd67,0x3bc93d7f,0x3c79bd78,0x3c48bd7b,0xbd043d5c,0x3d46bd22,0xbd713cac,0xbd6dbcc4,0x3d3e3d2c,0xbcf1bd62,0x3c163d7d,
0x3d6dbcc4,0xbd7dbc16,0x3d463d22,0xbcacbd71,0xbc483d7b,0x3d2cbd3e,0xbd753c95,0x3d783c79,0x3d80,0x3d04bd5c,0xbd623cf1,0x3d803b49,0xbd55bd0e,0x3cdb3d67,0x3bc9bd7f,0xbd183d4e,
0xbcc43d6d,0x3d4ebd18,0xbd7f3bc9,0x3d673cdb,0xbd0ebd55,0x3b493d80,0x3cf1bd62,0xbd5c3d04,0xbd35bd35,0x3c793d78,0x3c95bd75,0xbd3e3d2c,0x3d7bbc48,0xbd71bcac,0x3d223d46,0xbc16bd7d,
0xbd0ebd55,0xbc163d7d,0x3d46bd22,0xbd80bb49,0x3cc43d6d,0x3cacbd71,0xbd623cf1,0x3d783c79,0xbc48bd7b,0xbd043d5c,0x3d75bc95,0xbd67bcdb,0x3d80,0x3d2cbd3e,0xbd7f3bc9,0x3d4e3d18,
0xbd7bbc48,0x3d183d4e,0x3bc9bd7f,0xbd3e3d2c,0x3d6d3cc4,0xbcdbbd67,0xbc953d75,0x3d5cbd04,0xbd55bd0e,0x3c793d78,0x3cf1bd62,0xbd713cac,0x3d353d35,0xbb49bd80,0xbd223d46,0x3d7dbc16,
0xbd35bd35,0xbc163d7d,0x3d62bcf1,0xbd67bcdb,0x3c483d7b,0x3d2cbd3e,0xbd7fbbc9,0x3d043d5c,0x3cc4bd6d,0xbd783c79,0x3d463d22,0x3b49bd80,0xbd553d0e,0x3d713cac,0xbc95bd75,0xbd183d4e,
0x3d80,0x3d4ebd18,0xbd75bc95,0x3cac3d71,0x3d0ebd55,0xbd803b49,0x3d223d46,0x3c79bd78,0xbd6d3cc4,0x3d5c3d04,0xbbc9bd7f,0xbd3e3d2c,0x3d7b3c48,0xbcdbbd67,0xbcf13d62,0x3d7dbc16,
0x3d0ebd55,0xbd7dbc16,0x3c953d75,0x3d3ebd2c,0x3d353d35,0x3cacbd71,0xbd7f3bc9,0x3d043d5c,0xbc483d7b,0x3d78bc79,0xbd22bd46,0xbcdb3d67,0xbd6dbcc4,0x3b493d80,0x3d62bcf1,0xbd4ebd18,
0x3d7bbc48,0xbd18bd4e,0xbcf13d62,0x3d803b49,0x3d80,0x3d67bcdb,0xbd46bd22,0xbc793d78,0xbd553d0e,0x3d5c3d04,0x3bc9bd7f,0xbd713cac,0xbcc4bd6d,0xbd2c3d3e,0x3d753c95,0xbc16bd7d,
0xbcc43d6d,0x3d7d3c16,0xbbc9bd7f,0xbd713cac,0x3d0e3d55,0x3d2cbd3e,0xbd62bcf1,0xbc793d78,0xbd35bd35,0xbd043d5c,0x3d753c95,0x3b49bd80,0xbd7b3c48,0x3cdb3d67,0x3d46bd22,0xbd4ebd18,
0x3d6dbcc4,0xbd18bd4e,0xbd223d46,0x3d673cdb,0x3c48bd7b,0xbd803b49,0x3c953d75,0x3d5cbd04,0x3d80,0x3d78bc79,0xbcf1bd62,0xbd3e3d2c,0x3d553d0e,0x3cacbd71,0xbd7fbbc9,0x3c163d7d,
0x3d7b3c48,0x3c16bd7d,0xbd7fbbc9,0xbb493d80,0x3d6d3cc4,0x3cacbd71,0xbd75bc95,0xbc793d78,0x3d553d0e,0x3d04bd5c,0xbd62bcf1,0xbcdb3d67,0x3d353d35,0x3d2cbd3e,0xbd46bd22,0xbd183d4e,
0x3d0e3d55,0x3d4ebd18,0xbd22bd46,0xbd3e3d2c,0x3cc43d6d,0x3d67bcdb,0xbcf1bd62,0xbd5c3d04,0x3c483d7b,0x3d78bc79,0xbc95bd75,0xbd713cac,0x3d80,0x3d80bb49,0xbbc9bd7f,0xbd7d3c16,
0xbd800000,0x3d7d3c16,0xbd75bc95,0x3d673cdb,0xbd55bd0e,0x3d3e3d2c,0xbd22bd46,0x3d043d5c,0xbcc4bd6d,0x3c793d78,0xbbc9bd7f,0xbb493d80,0x3c48bd7b,0xbcac3d71,0x3cf1bd62,0xbd183d4e,
0x3d35bd35,0xbd4e3d18,0x3d62bcf1,0xbd713cac,0x3d7bbc48,0xbd803b49,0x3d7f3bc9,0xbd78bc79,0x3d6d3cc4,0xbd5cbd04,0x3d463d22,0xbd2cbd3e,0x3d0e3d55,0xbcdbbd67,0x3c953d75,0xbc16bd7d,
0xbc48bd7b,0xbc163d7d,0x3cf1bd62,0xbd3e3d2c,0xbd800000,0x3d713cac,0xbd46bd22,0x3d043d5c,0x3d0e3d55,0xbc79bd78,0xbbc93d7f,0x3cdbbd67,0x3d6dbcc4,0xbd803b49,0x3d753c95,0xbd4ebd18,
0xbd55bd0e,0x3d183d4e,0xbc95bd75,0xbb493d80,0xbd353d35,0x3d67bcdb,0xbd7f3bc9,0x3d783c79,0x3d7b3c48,0xbd5cbd04,0x3d223d46,0xbcacbd71,0x3cc4bd6d,0xbd2c3d3e,0x3d62bcf1,0xbd7d3c16,
0x3cc43d6d,0x3c16bd7d,0xbd223d46,0x3d71bcac,0xbd7bbc48,0x3d3e3d2c,0xbc95bd75,0xbc793d78,0xbd800000,0x3d5c3d04,0xbcf1bd62,0xbb493d80,0x3d0ebd55,0xbd673cdb,0x3d7f3bc9,0xbd4ebd18,
0xbd6dbcc4,0x3d183d4e,0xbbc9bd7f,0xbcdb3d67,0x3d55bd0e,0xbd803b49,0x3d623cf1,0xbd04bd5c,0x3d35bd35,0xbd783c79,0x3d753c95,0xbd2cbd3e,0x3c483d7b,0x3cacbd71,0xbd463d22,0x3d7dbc16,
0x3d55bd0e,0xbd7dbc16,0x3d223d46,0x3b49bd80,0xbd6d3cc4,0x3d713cac,0xbcf1bd62,0xbc793d78,0x3d7bbc48,0xbd5cbd04,0x3c953d75,0x3cdbbd67,0xbd800000,0x3d3e3d2c,0xbbc9bd7f,0xbd183d4e,
0x3c48bd7b,0xbd4e3d18,0x3d7f3bc9,0xbd2cbd3e,0xbcc43d6d,0x3d67bcdb,0xbd75bc95,0x3d043d5c,0x3d0ebd55,0xbd783c79,0x3d623cf1,0xbcacbd71,0xbd353d35,0x3d80bb49,0xbd46bd22,0x3c163d7d,
0x3d35bd35,0xbd7dbc16,0x3cf13d62,0x3cdbbd67,0xbd7b3c48,0x3d3e3d2c,0x3bc9bd7f,0xbd5c3d04,0x3d6d3cc4,0xbc79bd78,0xbd223d46,0x3d803b49,0xbd0ebd55,0xbcac3d71,0x3d75bc95,0xbd4ebd18,
0xbd800000,0x3d183d4e,0x3c95bd75,0xbd713cac,0x3d553d0e,0xbb49bd80,0xbd463d22,0x3d783c79,0xbcc4bd6d,0xbd043d5c,0x3d7fbbc9,0xbd2cbd3e,0xbc483d7b,0x3d67bcdb,0xbd62bcf1,0x3c163d7d,
0x3d553d0e,0x3c16bd7d,0xbd753c95,0x3d2c3d3e,0xbd353d35,0x3d713cac,0xbbc9bd7f,0xbd5c3d04,0xbd7bbc48,0x3c793d78,0x3d46bd22,0xbd67bcdb,0x3cc4bd6d,0xbd803b49,0x3cf13d62,0x3d18bd4e,
0x3c483d7b,0x3d4ebd18,0xbd62bcf1,0xbb493d80,0xbd800000,0x3cdb3d67,0x3d22bd46,0xbd78bc79,0xbd0ebd55,0xbd043d5c,0x3d7f3bc9,0xbcacbd71,0x3d6dbcc4,0xbd3ebd2c,0xbc953d75,0x3d7dbc16,
0xbd6dbcc4,0xbc163d7d,0x3d7fbbc9,0xbcacbd71,0xbd553d0e,0x3d3e3d2c,0x3cf1bd62,0xbd78bc79,0x3d35bd35,0xbd5cbd04,0xbc953d75,0x3d803b49,0xbc48bd7b,0xbd673cdb,0x3d223d46,0x3d18bd4e,
0x3cc43d6d,0x3d4ebd18,0xbd46bd22,0xbcdb3d67,0x3d7b3c48,0xbb49bd80,0xbd753c95,0x3d043d5c,0xbd800000,0x3c793d78,0x3d62bcf1,0xbd2cbd3e,0xbd0e3d55,0x3d713cac,0x3bc9bd7f,0xbd7d3c16,
0xbc483d7b,0x3d7d3c16,0x3bc9bd7f,0xbd80bb49,0xbcc43d6d,0x3d713cac,0x3c95bd75,0xbd78bc79,0xbd0e3d55,0x3d5c3d04,0x3cf1bd62,0xbd67bcdb,0xbd353d35,0x3d3e3d2c,0x3d22bd46,0xbd4ebd18,
0xbd553d0e,0x3d183d4e,0x3d46bd22,0xbd2cbd3e,0xbd6d3cc4,0x3cdb3d67,0x3d62bcf1,0xbd04bd5c,0xbd7b3c48,0x3c793d78,0x3d75bc95,0xbcacbd71,0xbd800000,0x3b493d80,0x3d7fbbc9,0xbc16bd7d,
0x3d80,0x3d7d3c16,0x3c95bd75,0xbd67bcdb,0xbd0e3d55,0x3d3e3d2c,0x3d46bd22,0xbd04bd5c,0xbd6d3cc4,0x3c793d78,0x3d7fbbc9,0x3b49bd80,0xbd7bbc48,0xbcac3d71,0x3d623cf1,0x3d18bd4e,
0xbd35bd35,0xbd4e3d18,0x3cf13d62,0x3d71bcac,0xbc48bd7b,0xbd803b49,0xbbc93d7f,0x3d783c79,0x3cc4bd6d,0xbd5cbd04,0xbd223d46,0x3d2c3d3e,0x3d55bd0e,0xbcdbbd67,0xbd753c95,0x3c163d7d,
0xbd7b3c48,0xbc163d7d,0x3d623cf1,0x3d3ebd2c,0x3d80,0x3d713cac,0x3d22bd46,0xbd04bd5c,0x3d55bd0e,0xbc79bd78,0xbd7fbbc9,0xbcdb3d67,0xbcc4bd6d,0xbd803b49,0xbc953d75,0x3d4e3d18,
0xbd0e3d55,0x3d183d4e,0x3d75bc95,0x3b49bd80,0x3d353d35,0x3d67bcdb,0xbbc9bd7f,0xbd78bc79,0x3c48bd7b,0xbd5cbd04,0xbd463d22,0x3cac3d71,0xbd6dbcc4,0xbd2c3d3e,0x3cf13d62,0x3d7dbc16,
0x3d6dbcc4,0x3c16bd7d,0xbd46bd22,0xbd713cac,0xbc483d7b,0x3d3e3d2c,0x3d75bc95,0x3c79bd78,0x3d80,0x3d5c3d04,0x3d62bcf1,0x3b49bd80,0xbd55bd0e,0xbd673cdb,0xbbc93d7f,0x3d4e3d18,
0xbcc43d6d,0x3d183d4e,0x3d7fbbc9,0x3cdbbd67,0xbd0ebd55,0xbd803b49,0xbcf13d62,0x3d043d5c,0xbd35bd35,0xbd783c79,0xbc953d75,0x3d2c3d3e,0x3d7bbc48,0x3cacbd71,0xbd22bd46,0xbd7d3c16,
0xbd0ebd55,0xbd7dbc16,0xbd463d22,0xbb493d80,0x3cc43d6d,0x3d713cac,0x3d62bcf1,0x3c79bd78,0xbc48bd7b,0xbd5cbd04,0xbd753c95,0xbcdb3d67,0x3d80,0x3d3e3d2c,0x3d7fbbc9,0x3d18bd4e,
0xbd7bbc48,0xbd4e3d18,0xbbc93d7f,0x3d2c3d3e,0x3d6d3cc4,0x3d67bcdb,0x3c95bd75,0xbd04bd5c,0xbd55bd0e,0xbd783c79,0xbcf13d62,0x3cac3d71,0x3d353d35,0x3d80bb49,0x3d22bd46,0xbc16bd7d,
0xbd35bd35,0xbd7dbc16,0xbd623cf1,0xbcdb3d67,0x3c483d7b,0x3d3e3d2c,0x3d7f3bc9,0x3d5cbd04,0x3cc4bd6d,0xbc79bd78,0xbd46bd22,0xbd80bb49,0xbd553d0e,0xbcac3d71,0x3c953d75,0x3d4e3d18,
0x3d80,0x3d183d4e,0x3d753c95,0x3d71bcac,0x3d0ebd55,0xbb49bd80,0xbd22bd46,0xbd78bc79,0xbd6d3cc4,0xbd043d5c,0x3bc93d7f,0x3d2c3d3e,0x3d7b3c48,0x3d67bcdb,0x3cf1bd62,0xbc16bd7d,
0x3d0ebd55,0x3c16bd7d,0xbc95bd75,0xbd2cbd3e,0x3d353d35,0x3d713cac,0x3d7fbbc9,0x3d5cbd04,0xbc483d7b,0x3c793d78,0x3d223d46,0x3d673cdb,0xbd6dbcc4,0xbd803b49,0xbd623cf1,0xbd183d4e,
0x3d7bbc48,0x3d4ebd18,0x3cf1bd62,0x3b49bd80,0x3d80,0x3cdb3d67,0x3d463d22,0x3d783c79,0xbd553d0e,0xbd043d5c,0xbbc93d7f,0x3cac3d71,0xbcc4bd6d,0xbd3ebd2c,0xbd75bc95,0xbd7d3c16,
0xbcc43d6d,0xbc163d7d,0x3bc93d7f,0x3cac3d71,0x3d0e3d55,0x3d3e3d2c,0x3d623cf1,0x3d783c79,0xbd35bd35,0xbd5cbd04,0xbd75bc95,0xbd80bb49,0xbd7b3c48,0xbd673cdb,0xbd463d22,0xbd183d4e,
0x3d6dbcc4,0x3d4ebd18,0x3d22bd46,0x3cdbbd67,0x3c48bd7b,0xbb49bd80,0xbc95bd75,0xbd04bd5c,0x3d80,0x3c793d78,0x3cf13d62,0x3d2c3d3e,0x3d553d0e,0x3d713cac,0x3d7f3bc9,0x3d7dbc16,
0x3d7b3c48,0x3d7d3c16,0x3d7f3bc9,0x3d803b49,0x3d6d3cc4,0x3d713cac,0x3d753c95,0x3d783c79,0x3d553d0e,0x3d5c3d04,0x3d623cf1,0x3d673cdb,0x3d353d35,0x3d3e3d2c,0x3d463d22,0x3d4e3d18,
0x3d0e3d55,0x3d183d4e,0x3d223d46,0x3d2c3d3e,0x3cc43d6d,0x3cdb3d67,0x3cf13d62,0x3d043d5c,0x3c483d7b,0x3c793d78,0x3c953d75,0x3cac3d71,0x3d80,0x3b493d80,0x3bc93d7f,0x3c163d7d,
0xbd800000,0xbc163d7d,0x3d753c95,0x3cdbbd67,0xbd55bd0e,0xbd2c3d3e,0x3d223d46,0x3d5cbd04,0xbcc4bd6d,0xbd783c79,0x3bc93d7f,0x3d803b49,0x3c48bd7b,0xbd71bcac,0xbcf13d62,0x3d4e3d18,
0x3d35bd35,0xbd18bd4e,0xbd623cf1,0x3cac3d71,0x3d7bbc48,0xbb49bd80,0xbd7fbbc9,0xbc793d78,0x3d6d3cc4,0x3d04bd5c,0xbd46bd22,0xbd3e3d2c,0x3d0e3d55,0x3d67bcdb,0xbc95bd75,0xbd7d3c16,
0xbc48bd7b,0xbd7dbc16,0xbcf13d62,0x3d2c3d3e,0xbd800000,0xbcac3d71,0x3d463d22,0x3d5cbd04,0x3d0e3d55,0x3d78bc79,0x3bc9bd7f,0xbd67bcdb,0x3d6dbcc4,0xbb49bd80,0xbd75bc95,0xbd183d4e,
0xbd55bd0e,0xbd4e3d18,0x3c953d75,0x3d803b49,0xbd353d35,0x3cdb3d67,0x3d7fbbc9,0x3c79bd78,0x3d7b3c48,0x3d04bd5c,0xbd22bd46,0xbd713cac,0x3cc4bd6d,0xbd3ebd2c,0xbd623cf1,0x3c163d7d,
0x3cc43d6d,0x3d7d3c16,0x3d22bd46,0xbcacbd71,0xbd7bbc48,0xbd2c3d3e,0x3c953d75,0x3d783c79,0xbd800000,0xbd043d5c,0x3cf13d62,0x3d803b49,0x3d0ebd55,0xbcdbbd67,0xbd7fbbc9,0xbd183d4e,
0xbd6dbcc4,0xbd4e3d18,0x3bc93d7f,0x3d673cdb,0x3d55bd0e,0xbb49bd80,0xbd62bcf1,0xbd5c3d04,0x3d35bd35,0xbc79bd78,0xbd75bc95,0xbd3e3d2c,0x3c483d7b,0x3d713cac,0x3d46bd22,0xbc16bd7d,
0x3d55bd0e,0x3c16bd7d,0xbd22bd46,0xbd80bb49,0xbd6d3cc4,0xbcac3d71,0x3cf13d62,0x3d783c79,0x3d7bbc48,0x3d04bd5c,0xbc95bd75,0xbd67bcdb,0xbd800000,0xbd2c3d3e,0x3bc93d7f,0x3d4e3d18,
0x3c48bd7b,0xbd18bd4e,0xbd7fbbc9,0xbd3e3d2c,0xbcc43d6d,0x3cdb3d67,0x3d753c95,0x3d5cbd04,0x3d0ebd55,0xbc79bd78,0xbd62bcf1,0xbd713cac,0xbd353d35,0x3b493d80,0x3d463d22,0x3d7dbc16,
0x3d35bd35,0x3c16bd7d,0xbcf1bd62,0xbd67bcdb,0xbd7b3c48,0xbd2c3d3e,0xbbc93d7f,0x3d043d5c,0x3d6d3cc4,0x3d78bc79,0x3d22bd46,0x3b49bd80,0xbd0ebd55,0xbd71bcac,0xbd753c95,0xbd183d4e,
0xbd800000,0xbd4e3d18,0xbc953d75,0x3cac3d71,0x3d553d0e,0x3d80bb49,0x3d46bd22,0x3c79bd78,0xbcc4bd6d,0xbd5cbd04,0xbd7f3bc9,0xbd3e3d2c,0xbc483d7b,0x3cdb3d67,0x3d623cf1,0x3d7dbc16,
0x3d553d0e,0x3d7d3c16,0x3d75bc95,0x3d3ebd2c,0xbd353d35,0xbcac3d71,0x3bc93d7f,0x3d043d5c,0xbd7bbc48,0xbd783c79,0xbd463d22,0xbcdb3d67,0x3cc4bd6d,0xbb49bd80,0xbcf1bd62,0xbd4ebd18,
0x3c483d7b,0x3d183d4e,0x3d623cf1,0x3d803b49,0xbd800000,0xbd673cdb,0xbd223d46,0xbc793d78,0xbd0ebd55,0xbd5cbd04,0xbd7fbbc9,0xbd713cac,0x3d6dbcc4,0x3d2cbd3e,0x3c95bd75,0xbc16bd7d,
0xbd6dbcc4,0xbd7dbc16,0xbd7f3bc9,0xbd713cac,0xbd553d0e,0xbd2c3d3e,0xbcf13d62,0xbc793d78,0x3d35bd35,0x3d04bd5c,0x3c95bd75,0x3b49bd80,0xbc48bd7b,0xbcdbbd67,0xbd22bd46,0xbd4ebd18,
0x3cc43d6d,0x3d183d4e,0x3d463d22,0x3d673cdb,0x3d7b3c48,0x3d80bb49,0x3d75bc95,0x3d5cbd04,0xbd800000,0xbd783c79,0xbd623cf1,0xbd3e3d2c,0xbd0e3d55,0xbcac3d71,0xbbc93d7f,0x3c163d7d,
0xbc483d7b,0xbc163d7d,0xbbc93d7f,0xbb493d80,0xbcc43d6d,0xbcac3d71,0xbc953d75,0xbc793d78,0xbd0e3d55,0xbd043d5c,0xbcf13d62,0xbcdb3d67,0xbd353d35,0xbd2c3d3e,0xbd223d46,0xbd183d4e,
0xbd553d0e,0xbd4e3d18,0xbd463d22,0xbd3e3d2c,0xbd6d3cc4,0xbd673cdb,0xbd623cf1,0xbd5c3d04,0xbd7b3c48,0xbd783c79,0xbd753c95,0xbd713cac,0xbd800000,0xbd803b49,0xbd7f3bc9,0xbd7d3c16,
0x3f003f00,0xbf003f00,0x3f003f00,0xbf003f00,0x3f003f00,0xbf003f00,0x3f003f00,0xbf003f00,0x3f003f00,0xbf003f00,0x3f003f00,0xbf003f00,0x3f003f00,0xbf003f00,0x3f003f00,0xbf003f00,
0x3eff3f00,0xbd490000,0x3ea23eb5,0xbec6beb5,0x3ef53efb,0xbe15bdc8,0x3e713e8e,0xbee2bed5,0x3ee23eed,0xbe71be44,0x3e153e44,0xbef5beed,0x3ec63ed5,0xbea2be8e,0x3d493dc8,0xbeffbefb,
0x3efb3f00,0xbdc80000,0xbdc80000,0xbefbbf00,0x3ed53eed,0xbe8ebe44,0xbe8ebe44,0xbed5beed,0x3e8e3eb5,0xbed5beb5,0xbed5beb5,0xbe8ebeb5,0x3dc83e44,0xbefbbeed,0xbefbbeed,0xbdc8be44,
0x3ef53f00,0xbe150000,0xbee2beb5,0xbe71beb5,0x3ea23ed5,0xbec6be8e,0xbeffbefb,0x3d49bdc8,0x3d493e44,0xbeffbeed,0xbec6beed,0x3ea23e44,0xbe71bdc8,0xbee2befb,0xbe15be8e,0x3ef53ed5,
0x3eed3f00,0xbe440000,0xbeedbf00,0x3e440000,0x3e443eb5,0xbeedbeb5,0xbe44beb5,0x3eed3eb5,0xbe440000,0xbeedbf00,0x3e440000,0x3eed3f00,0xbeedbeb5,0xbe44beb5,0x3eed3eb5,0x3e443eb5,
0x3ee23f00,0xbe710000,0xbe15beb5,0x3ef53eb5,0x3d493e8e,0xbeffbed5,0x3ea23dc8,0x3ec63efb,0xbec6be44,0xbea2beed,0x3eff3eed,0xbd493e44,0xbef5befb,0x3e15bdc8,0x3e713ed5,0xbee2be8e,
0x3ed53f00,0xbe8e0000,0x3e8e0000,0x3ed53f00,0xbdc83e44,0xbefbbeed,0x3efb3eed,0xbdc83e44,0xbefbbeb5,0xbdc8beb5,0x3dc83eb5,0xbefbbeb5,0xbe8ebeed,0x3ed53e44,0xbed5be44,0xbe8ebeed,
0x3ec63f00,0xbea20000,0x3eff3eb5,0x3d493eb5,0xbe713dc8,0xbee2befb,0x3e153ed5,0xbef5be8e,0xbef5beed,0x3e15be44,0xbee2be44,0xbe71beed,0x3d49be8e,0x3eff3ed5,0xbea2befb,0x3ec63dc8,
0x3f00,0xbf000000,0x3f00,0xbf000000,0xbf00,0x3f000000,0xbf00,0x3f000000,0x3f00,0xbf000000,0x3f00,0xbf000000,0xbf00,0x3f000000,0xbf00,0x3f000000,
0xbd493f00,0xbeff0000,0xbec63eb5,0xbea2beb5,0x3e15befb,0x3ef53dc8,0x3ee2be8e,0x3e713ed5,0xbe713eed,0xbee2be44,0xbef53e44,0xbe15beed,0x3ea2bed5,0x3ec63e8e,0x3effbdc8,0x3d493efb,
0xbdc83f00,0xbefb0000,0xbefb0000,0x3dc8bf00,0x3e8ebeed,0x3ed53e44,0x3ed53e44,0xbe8e3eed,0xbed53eb5,0xbe8ebeb5,0xbe8ebeb5,0x3ed5beb5,0x3efbbe44,0x3dc83eed,0x3dc83eed,0xbefb3e44,
0xbe153f00,0xbef50000,0xbe71beb5,0x3ee2beb5,0x3ec6bed5,0x3ea23e8e,0xbd493efb,0xbeff3dc8,0xbeff3e44,0xbd49beed,0x3ea2beed,0x3ec63e44,0x3ee23dc8,0xbe713efb,0xbef53e8e,0xbe15bed5,
0xbe443f00,0xbeed0000,0x3e44bf00,0x3eed0000,0x3eedbeb5,0x3e443eb5,0xbeed3eb5,0xbe44beb5,0xbeed0000,0x3e44bf00,0x3eed0000,0xbe443f00,0x3e443eb5,0xbeed3eb5,0xbe44beb5,0x3eedbeb5,
0xbe713f00,0xbee20000,0x3ef5beb5,0x3e153eb5,0x3effbe8e,0x3d493ed5,0xbec6bdc8,0x3ea2befb,0xbea2be44,0x3ec6beed,0xbd493eed,0xbeff3e44,0xbe153efb,0xbef53dc8,0x3ee2bed5,0x3e713e8e,
0xbe8e3f00,0xbed50000,0x3ed50000,0xbe8e3f00,0x3efbbe44,0xbdc83eed,0x3dc8beed,0x3efbbe44,0xbdc8beb5,0x3efbbeb5,0xbefb3eb5,0xbdc8beb5,0xbed53eed,0xbe8ebe44,0x3e8e3e44,0xbed53eed,
0xbea23f00,0xbec60000,0x3d493eb5,0xbeff3eb5,0x3ee2bdc8,0xbe713efb,0x3ef5bed5,0x3e153e8e,0x3e15beed,0x3ef5be44,0xbe71be44,0x3ee2beed,0xbeff3e8e,0x3d49bed5,0xbec63efb,0xbea2bdc8,
0x3eb53f00,0xbeb50000,0x3eb53f00,0xbeb50000,0xbeb50000,0xbeb5bf00,0xbeb50000,0xbeb5bf00,0xbeb5bf00,0x3eb50000,0xbeb5bf00,0x3eb50000,0x3eb50000,0x3eb53f00,0x3eb50000,0x3eb53f00,
0xbeff3f00,0x3d490000,0xbea23eb5,0x3ec6beb5,0xbef53efb,0x3e15bdc8,0xbe713e8e,0x3ee2bed5,0xbee23eed,0x3e71be44,0xbe153e44,0x3ef5beed,0xbec63ed5,0x3ea2be8e,0xbd493dc8,0x3effbefb,
0xbefb3f00,0x3dc80000,0x3dc80000,0x3efbbf00,0xbed53eed,0x3e8ebe44,0x3e8ebe44,0x3ed5beed,0xbe8e3eb5,0x3ed5beb5,0x3ed5beb5,0x3e8ebeb5,0xbdc83e44,0x3efbbeed,0x3efbbeed,0x3dc8be44,
0xbef53f00,0x3e150000,0x3ee2beb5,0x3e71beb5,0xbea23ed5,0x3ec6be8e,0x3effbefb,0xbd49bdc8,0xbd493e44,0x3effbeed,0x3ec6beed,0xbea23e44,0x3e71bdc8,0x3ee2befb,0x3e15be8e,0xbef53ed5,
0xbeed3f00,0x3e440000,0x3eedbf00,0xbe440000,0xbe443eb5,0x3eedbeb5,0x3e44beb5,0xbeed3eb5,0x3e440000,0x3eedbf00,0xbe440000,0xbeed3f00,0x3eedbeb5,0x3e44beb5,0xbeed3eb5,0xbe443eb5,
0xbee23f00,0x3e710000,0x3e15beb5,0xbef53eb5,0xbd493e8e,0x3effbed5,0xbea23dc8,0xbec63efb,0x3ec6be44,0x3ea2beed,0xbeff3eed,0x3d493e44,0x3ef5befb,0xbe15bdc8,0xbe713ed5,0x3ee2be8e,
0xbed53f00,0x3e8e0000,0xbe8e0000,0xbed53f00,0x3dc83e44,0x3efbbeed,0xbefb3eed,0x3dc83e44,0x3efbbeb5,0x3dc8beb5,0xbdc83eb5,0x3efbbeb5,0x3e8ebeed,0xbed53e44,0x3ed5be44,0x3e8ebeed,
0xbec63f00,0x3ea20000,0xbeff3eb5,0xbd493eb5,0x3e713dc8,0x3ee2befb,0xbe153ed5,0x3ef5be8e,0x3ef5beed,0xbe15be44,0x3ee2be44,0x3e71beed,0xbd49be8e,0xbeff3ed5,0x3ea2befb,0xbec63dc8,
0xbeb53f00,0xbeb50000,0xbeb53f00,0xbeb50000,0x3eb50000,0xbeb53f00,0x3eb50000,0xbeb53f00,0x3eb5bf00,0x3eb50000,0x3eb5bf00,0x3eb50000,0xbeb50000,0x3eb5bf00,0xbeb50000,0x3eb5bf00,
0x3d493f00,0x3eff0000,0x3ec63eb5,0x3ea2beb5,0xbe15befb,0xbef53dc8,0xbee2be8e,0xbe713ed5,0x3e713eed,0x3ee2be44,0x3ef53e44,0x3e15beed,0xbea2bed5,0xbec63e8e,0xbeffbdc8,0xbd493efb,
0x3dc83f00,0x3efb0000,0x3efb0000,0xbdc8bf00,0xbe8ebeed,0xbed53e44,0xbed53e44,0x3e8e3eed,0x3ed53eb5,0x3e8ebeb5,0x3e8ebeb5,0xbed5beb5,0xbefbbe44,0xbdc83eed,0xbdc83eed,0x3efb3e44,
0x3e153f00,0x3ef50000,0x3e71beb5,0xbee2beb5,0xbec6bed5,0xbea23e8e,0x3d493efb,0x3eff3dc8,0x3eff3e44,0x3d49beed,0xbea2beed,0xbec63e44,0xbee23dc8,0x3e713efb,0x3ef53e8e,0x3e15bed5,
0x3e443f00,0x3eed0000,0xbe44bf00,0xbeed0000,0xbeedbeb5,0xbe443eb5,0x3eed3eb5,0x3e44beb5,0x3eed0000,0xbe44bf00,0xbeed0000,0x3e443f00,0xbe443eb5,0x3eed3eb5,0x3e44beb5,0xbeedbeb5,
0x3e713f00,0x3ee20000,0xbef5beb5,0xbe153eb5,0xbeffbe8e,0xbd493ed5,0x3ec6bdc8,0xbea2befb,0x3ea2be44,0xbec6beed,0x3d493eed,0x3eff3e44,0x3e153efb,0x3ef53dc8,0xbee2bed5,0xbe713e8e,
0x3e8e3f00,0x3ed50000,0xbed50000,0x3e8e3f00,0xbefbbe44,0x3dc83eed,0xbdc8beed,0xbefbbe44,0x3dc8beb5,0xbefbbeb5,0x3efb3eb5,0x3dc8beb5,0x3ed53eed,0x3e8ebe44,0xbe8e3e44,0x3ed53eed,
0x3ea23f00,0x3ec60000,0xbd493eb5,0x3eff3eb5,0xbee2bdc8,0x3e713efb,0xbef5bed5,0xbe153e8e,0xbe15beed,0xbef5be44,0x3e71be44,0xbee2beed,0x3eff3e8e,0xbd49bed5,0x3ec63efb,0x3ea2bdc8,
0x3f003f00,0xbf003f00,0x3f003f00,0xbf003f00,0x3f003f00,0xbf003f00,0x3f003f00,0xbf003f00,0x3f003f00,0xbf003f00,0x3f003f00,0xbf003f00,0x3f003f00,0xbf003f00,0x3f003f00,0xbf003f00,
0xbd490000,0xbeffbf00,0xbec6beb5,0xbea2beb5,0xbe15bdc8,0xbef5befb,0xbee2bed5,0xbe71be8e,0xbe71be44,0xbee2beed,0xbef5beed,0xbe15be44,0xbea2be8e,0xbec6bed5,0xbeffbefb,0xbd49bdc8,
0xbefbbf00,0x3dc80000,0x3dc80000,0x3efb3f00,0xbed5beed,0x3e8e3e44,0x3e8e3e44,0x3ed53eed,0xbe8ebeb5,0x3ed53eb5,0x3ed53eb5,0x3e8e3eb5,0xbdc8be44,0x3efb3eed,0x3efb3eed,0x3dc83e44,
0x3e150000,0x3ef53f00,0x3e713eb5,0xbee2beb5,0x3ec63e8e,0x3ea23ed5,0xbd493dc8,0xbeffbefb,0x3eff3eed,0x3d493e44,0xbea2be44,0xbec6beed,0x3ee23efb,0xbe71bdc8,0xbef5bed5,0xbe15be8e,
0x3eed3f00,0xbe440000,0xbeedbf00,0x3e440000,0x3e443eb5,0xbeedbeb5,0xbe44beb5,0x3eed3eb5,0xbe440000,0xbeedbf00,0x3e440000,0x3eed3f00,0xbeedbeb5,0xbe44beb5,0x3eed3eb5,0x3e443eb5,
0xbe710000,0xbee2bf00,0x3ef53eb5,0x3e153eb5,0xbeffbed5,0xbd49be8e,0x3ec63efb,0xbea2bdc8,0xbea2beed,0x3ec63e44,0xbd493e44,0xbeffbeed,0x3e15bdc8,0x3ef53efb,0xbee2be8e,0xbe71bed5,
0xbed5bf00,0x3e8e0000,0xbe8e0000,0xbed5bf00,0x3dc8be44,0x3efb3eed,0xbefbbeed,0x3dc8be44,0x3efb3eb5,0x3dc83eb5,0xbdc8beb5,0x3efb3eb5,0x3e8e3eed,0xbed5be44,0x3ed53e44,0x3e8e3eed,
0x3ea20000,0x3ec63f00,0xbd49beb5,0x3eff3eb5,0x3ee23efb,0xbe713dc8,0x3ef53e8e,0x3e153ed5,0xbe153e44,0xbef5beed,0x3e713eed,0xbee2be44,0xbeffbed5,0x3d49be8e,0xbec6bdc8,0xbea2befb,
0x3f00,0xbf000000,0x3f00,0xbf000000,0xbf00,0x3f000000,0xbf00,0x3f000000,0x3f00,0xbf000000,0x3f00,0xbf000000,0xbf00,0x3f000000,0xbf00,0x3f000000,
0xbeff0000,0x3d49bf00,0xbea2beb5,0x3ec6beb5,0x3ef53dc8,0xbe153efb,0x3e713ed5,0xbee23e8e,0xbee2be44,0x3e71beed,0xbe15beed,0x3ef5be44,0x3ec63e8e,0xbea23ed5,0x3d493efb,0xbeff3dc8,
0x3dc8bf00,0x3efb0000,0x3efb0000,0xbdc83f00,0xbe8e3eed,0xbed5be44,0xbed5be44,0x3e8ebeed,0x3ed5beb5,0x3e8e3eb5,0x3e8e3eb5,0xbed53eb5,0xbefb3e44,0xbdc8beed,0xbdc8beed,0x3efbbe44,
0x3ef50000,0xbe153f00,0xbee23eb5,0xbe71beb5,0xbea2be8e,0x3ec6bed5,0x3effbdc8,0xbd493efb,0x3d493eed,0xbeff3e44,0xbec6be44,0x3ea2beed,0x3e71befb,0x3ee23dc8,0x3e153ed5,0xbef53e8e,
0xbe443f00,0xbeed0000,0x3e44bf00,0x3eed0000,0x3eedbeb5,0x3e443eb5,0xbeed3eb5,0xbe44beb5,0xbeed0000,0x3e44bf00,0x3eed0000,0xbe443f00,0x3e443eb5,0xbeed3eb5,0xbe44beb5,0x3eedbeb5,
0xbee20000,0x3e71bf00,0x3e153eb5,0xbef53eb5,0x3d493ed5,0xbeff3e8e,0x3ea2befb,0x3ec63dc8,0x3ec6beed,0x3ea23e44,0xbeff3e44,0x3d49beed,0xbef53dc8,0x3e15befb,0x3e713e8e,0xbee23ed5,
0x3e8ebf00,0x3ed50000,0xbed50000,0x3e8ebf00,0xbefb3e44,0x3dc8beed,0xbdc83eed,0xbefb3e44,0x3dc83eb5,0xbefb3eb5,0x3efbbeb5,0x3dc83eb5,0x3ed5beed,0x3e8e3e44,0xbe8ebe44,0x3ed5beed,
0x3ec60000,0xbea23f00,0x3effbeb5,0x3d493eb5,0x3e71befb,0x3ee2bdc8,0xbe15be8e,0x3ef5bed5,0xbef53e44,0x3e15beed,0xbee23eed,0xbe71be44,0xbd493ed5,0xbeff3e8e,0x3ea23dc8,0xbec63efb,
0x3eb53f00,0xbeb50000,0x3eb53f00,0xbeb50000,0xbeb50000,0xbeb5bf00,0xbeb50000,0xbeb5bf00,0xbeb5bf00,0x3eb50000,0xbeb5bf00,0x3eb50000,0x3eb50000,0x3eb53f00,0x3eb50000,0x3eb53f00,
0x3d490000,0x3effbf00,0x3ec6beb5,0x3ea2beb5,0x3e15bdc8,0x3ef5befb,0x3ee2bed5,0x3e71be8e,0x3e71be44,0x3ee2beed,0x3ef5beed,0x3e15be44,0x3ea2be8e,0x3ec6bed5,0x3effbefb,0x3d49bdc8,
0x3efbbf00,0xbdc80000,0xbdc80000,0xbefb3f00,0x3ed5beed,0xbe8e3e44,0xbe8e3e44,0xbed53eed,0x3e8ebeb5,0xbed53eb5,0xbed53eb5,0xbe8e3eb5,0x3dc8be44,0xbefb3eed,0xbefb3eed,0xbdc83e44,
0xbe150000,0xbef53f00,0xbe713eb5,0x3ee2beb5,0xbec63e8e,0xbea23ed5,0x3d493dc8,0x3effbefb,0xbeff3eed,0xbd493e44,0x3ea2be44,0x3ec6beed,0xbee23efb,0x3e71bdc8,0x3ef5bed5,0x3e15be8e,
0xbeed3f00,0x3e440000,0x3eedbf00,0xbe440000,0xbe443eb5,0x3eedbeb5,0x3e44beb5,0xbeed3eb5,0x3e440000,0x3eedbf00,0xbe440000,0xbeed3f00,0x3eedbeb5,0x3e44beb5,0xbeed3eb5,0xbe443eb5,
0x3e710000,0x3ee2bf00,0xbef53eb5,0xbe153eb5,0x3effbed5,0x3d49be8e,0xbec63efb,0x3ea2bdc8,0x3ea2beed,0xbec63e44,0x3d493e44,0x3effbeed,0xbe15bdc8,0xbef53efb,0x3ee2be8e,0x3e71bed5,
0x3ed5bf00,0xbe8e0000,0x3e8e0000,0x3ed5bf00,0xbdc8be44,0xbefb3eed,0x3efbbeed,0xbdc8be44,0xbefb3eb5,0xbdc83eb5,0x3dc8beb5,0xbefb3eb5,0xbe8e3eed,0x3ed5be44,0xbed53e44,0xbe8e3eed,
0xbea20000,0xbec63f00,0x3d49beb5,0xbeff3eb5,0xbee23efb,0x3e713dc8,0xbef53e8e,0xbe153ed5,0x3e153e44,0x3ef5beed,0xbe713eed,0x3ee2be44,0x3effbed5,0xbd49be8e,0x3ec6bdc8,0x3ea2befb,
0xbeb53f00,0xbeb50000,0xbeb53f00,0xbeb50000,0x3eb50000,0xbeb53f00,0x3eb50000,0xbeb53f00,0x3eb5bf00,0x3eb50000,0x3eb5bf00,0x3eb50000,0xbeb50000,0x3eb5bf00,0xbeb50000,0x3eb5bf00,
0x3eff0000,0xbd49bf00,0x3ea2beb5,0xbec6beb5,0xbef53dc8,0x3e153efb,0xbe713ed5,0x3ee23e8e,0x3ee2be44,0xbe71beed,0x3e15beed,0xbef5be44,0xbec63e8e,0x3ea23ed5,0xbd493efb,0x3eff3dc8,
0xbdc8bf00,0xbefb0000,0xbefb0000,0x3dc83f00,0x3e8e3eed,0x3ed5be44,0x3ed5be44,0xbe8ebeed,0xbed5beb5,0xbe8e3eb5,0xbe8e3eb5,0x3ed53eb5,0x3efb3e44,0x3dc8beed,0x3dc8beed,0xbefbbe44,
0xbef50000,0x3e153f00,0x3ee23eb5,0x3e71beb5,0x3ea2be8e,0xbec6bed5,0xbeffbdc8,0x3d493efb,0xbd493eed,0x3eff3e44,0x3ec6be44,0xbea2beed,0xbe71befb,0xbee23dc8,0xbe153ed5,0x3ef53e8e,
0x3e443f00,0x3eed0000,0xbe44bf00,0xbeed0000,0xbeedbeb5,0xbe443eb5,0x3eed3eb5,0x3e44beb5,0x3eed0000,0xbe44bf00,0xbeed0000,0x3e443f00,0xbe443eb5,0x3eed3eb5,0x3e44beb5,0xbeedbeb5,
0x3ee20000,0xbe71bf00,0xbe153eb5,0x3ef53eb5,0xbd493ed5,0x3eff3e8e,0xbea2befb,0xbec63dc8,0xbec6beed,0xbea23e44,0x3eff3e44,0xbd49beed,0x3ef53dc8,0xbe15befb,0xbe713e8e,0x3ee23ed5,
0xbe8ebf00,0xbed50000,0x3ed50000,0xbe8ebf00,0x3efb3e44,0xbdc8beed,0x3dc83eed,0x3efb3e44,0xbdc83eb5,0x3efb3eb5,0xbefbbeb5,0xbdc83eb5,0xbed5beed,0xbe8e3e44,0x3e8ebe44,0xbed5beed,
0xbec60000,0x3ea23f00,0xbeffbeb5,0xbd493eb5,0xbe71befb,0xbee2bdc8,0x3e15be8e,0xbef5bed5,0x3ef53e44,0xbe15beed,0x3ee23eed,0x3e71be44,0x3d493ed5,0x3eff3e8e,0xbea23dc8,0x3ec63efb,
0x3f003f00,0xbf003f00,0x3f003f00,0xbf003f00,0x3f003f00,0xbf003f00,0x3f003f00,0xbf003f00,0x3f003f00,0xbf003f00,0x3f003f00,0xbf003f00,0x3f003f00,0xbf003f00,0x3f003f00,0xbf003f00,
0xbeffbf00,0x3d490000,0xbea2beb5,0x3ec63eb5,0xbef5befb,0x3e153dc8,0xbe71be8e,0x3ee23ed5,0xbee2beed,0x3e713e44,0xbe15be44,0x3ef53eed,0xbec6bed5,0x3ea23e8e,0xbd49bdc8,0x3eff3efb,
0x3efb3f00,0xbdc80000,0xbdc80000,0xbefbbf00,0x3ed53eed,0xbe8ebe44,0xbe8ebe44,0xbed5beed,0x3e8e3eb5,0xbed5beb5,0xbed5beb5,0xbe8ebeb5,0x3dc83e44,0xbefbbeed,0xbefbbeed,0xbdc8be44,
0xbef5bf00,0x3e150000,0x3ee23eb5,0x3e713eb5,0xbea2bed5,0x3ec63e8e,0x3eff3efb,0xbd493dc8,0xbd49be44,0x3eff3eed,0x3ec63eed,0xbea2be44,0x3e713dc8,0x3ee23efb,0x3e153e8e,0xbef5bed5,
0x3eed3f00,0xbe440000,0xbeedbf00,0x3e440000,0x3e443eb5,0xbeedbeb5,0xbe44beb5,0x3eed3eb5,0xbe440000,0xbeedbf00,0x3e440000,0x3eed3f00,0xbeedbeb5,0xbe44beb5,0x3eed3eb5,0x3e443eb5,
0xbee2bf00,0x3e710000,0x3e153eb5,0xbef5beb5,0xbd49be8e,0x3eff3ed5,0xbea2bdc8,0xbec6befb,0x3ec63e44,0x3ea23eed,0xbeffbeed,0x3d49be44,0x3ef53efb,0xbe153dc8,0xbe71bed5,0x3ee23e8e,
0x3ed53f00,0xbe8e0000,0x3e8e0000,0x3ed53f00,0xbdc83e44,0xbefbbeed,0x3efb3eed,0xbdc83e44,0xbefbbeb5,0xbdc8beb5,0x3dc83eb5,0xbefbbeb5,0xbe8ebeed,0x3ed53e44,0xbed5be44,0xbe8ebeed,
0xbec6bf00,0x3ea20000,0xbeffbeb5,0xbd49beb5,0x3e71bdc8,0x3ee23efb,0xbe15bed5,0x3ef53e8e,0x3ef53eed,0xbe153e44,0x3ee23e44,0x3e713eed,0xbd493e8e,0xbeffbed5,0x3ea23efb,0xbec6bdc8,
0x3f00,0xbf000000,0x3f00,0xbf000000,0xbf00,0x3f000000,0xbf00,0x3f000000,0x3f00,0xbf000000,0x3f00,0xbf000000,0xbf00,0x3f000000,0xbf00,0x3f000000,
0x3d49bf00,0x3eff0000,0x3ec6beb5,0x3ea23eb5,0xbe153efb,0xbef5bdc8,0xbee23e8e,0xbe71bed5,0x3e71beed,0x3ee23e44,0x3ef5be44,0x3e153eed,0xbea23ed5,0xbec6be8e,0xbeff3dc8,0xbd49befb,
0xbdc83f00,0xbefb0000,0xbefb0000,0x3dc8bf00,0x3e8ebeed,0x3ed53e44,0x3ed53e44,0xbe8e3eed,0xbed53eb5,0xbe8ebeb5,0xbe8ebeb5,0x3ed5beb5,0x3efbbe44,0x3dc83eed,0x3dc83eed,0xbefb3e44,
0x3e15bf00,0x3ef50000,0x3e713eb5,0xbee23eb5,0xbec63ed5,0xbea2be8e,0x3d49befb,0x3effbdc8,0x3effbe44,0x3d493eed,0xbea23eed,0xbec6be44,0xbee2bdc8,0x3e71befb,0x3ef5be8e,0x3e153ed5,
0xbe443f00,0xbeed0000,0x3e44bf00,0x3eed0000,0x3eedbeb5,0x3e443eb5,0xbeed3eb5,0xbe44beb5,0xbeed0000,0x3e44bf00,0x3eed0000,0xbe443f00,0x3e443eb5,0xbeed3eb5,0xbe44beb5,0x3eedbeb5,
0x3e71bf00,0x3ee20000,0xbef53eb5,0xbe15beb5,0xbeff3e8e,0xbd49bed5,0x3ec63dc8,0xbea23efb,0x3ea23e44,0xbec63eed,0x3d49beed,0x3effbe44,0x3e15befb,0x3ef5bdc8,0xbee23ed5,0xbe71be8e,
0xbe8e3f00,0xbed50000,0x3ed50000,0xbe8e3f00,0x3efbbe44,0xbdc83eed,0x3dc8beed,0x3efbbe44,0xbdc8beb5,0x3efbbeb5,0xbefb3eb5,0xbdc8beb5,0xbed53eed,0xbe8ebe44,0x3e8e3e44,0xbed53eed,
0x3ea2bf00,0x3ec60000,0xbd49beb5,0x3effbeb5,0xbee23dc8,0x3e71befb,0xbef53ed5,0xbe15be8e,0xbe153eed,0xbef53e44,0x3e713e44,0xbee23eed,0x3effbe8e,0xbd493ed5,0x3ec6befb,0x3ea23dc8,
0x3eb53f00,0xbeb50000,0x3eb53f00,0xbeb50000,0xbeb50000,0xbeb5bf00,0xbeb50000,0xbeb5bf00,0xbeb5bf00,0x3eb50000,0xbeb5bf00,0x3eb50000,0x3eb50000,0x3eb53f00,0x3eb50000,0x3eb53f00,
0x3effbf00,0xbd490000,0x3ea2beb5,0xbec63eb5,0x3ef5befb,0xbe153dc8,0x3e71be8e,0xbee23ed5,0x3ee2beed,0xbe713e44,0x3e15be44,0xbef53eed,0x3ec6bed5,0xbea23e8e,0x3d49bdc8,0xbeff3efb,
0xbefb3f00,0x3dc80000,0x3dc80000,0x3efbbf00,0xbed53eed,0x3e8ebe44,0x3e8ebe44,0x3ed5beed,0xbe8e3eb5,0x3ed5beb5,0x3ed5beb5,0x3e8ebeb5,0xbdc83e44,0x3efbbeed,0x3efbbeed,0x3dc8be44,
0x3ef5bf00,0xbe150000,0xbee23eb5,0xbe713eb5,0x3ea2bed5,0xbec63e8e,0xbeff3efb,0x3d493dc8,0x3d49be44,0xbeff3eed,0xbec63eed,0x3ea2be44,0xbe713dc8,0xbee23efb,0xbe153e8e,0x3ef5bed5,
0xbeed3f00,0x3e440000,0x3eedbf00,0xbe440000,0xbe443eb5,0x3eedbeb5,0x3e44beb5,0xbeed3eb5,0x3e440000,0x3eedbf00,0xbe440000,0xbeed3f00,0x3eedbeb5,0x3e44beb5,0xbeed3eb5,0xbe443eb5,
0x3ee2bf00,0xbe710000,0xbe153eb5,0x3ef5beb5,0x3d49be8e,0xbeff3ed5,0x3ea2bdc8,0x3ec6befb,0xbec63e44,0xbea23eed,0x3effbeed,0xbd49be44,0xbef53efb,0x3e153dc8,0x3e71bed5,0xbee23e8e,
0xbed53f00,0x3e8e0000,0xbe8e0000,0xbed53f00,0x3dc83e44,0x3efbbeed,0xbefb3eed,0x3dc83e44,0x3efbbeb5,0x3dc8beb5,0xbdc83eb5,0x3efbbeb5,0x3e8ebeed,0xbed53e44,0x3ed5be44,0x3e8ebeed,
0x3ec6bf00,0xbea20000,0x3effbeb5,0x3d49beb5,0xbe71bdc8,0xbee23efb,0x3e15bed5,0xbef53e8e,0xbef53eed,0x3e153e44,0xbee23e44,0xbe713eed,0x3d493e8e,0x3effbed5,0xbea23efb,0x3ec6bdc8,
0xbeb53f00,0xbeb50000,0xbeb53f00,0xbeb50000,0x3eb50000,0xbeb53f00,0x3eb50000,0xbeb53f00,0x3eb5bf00,0x3eb50000,0x3eb5bf00,0x3eb50000,0xbeb50000,0x3eb5bf00,0xbeb50000,0x3eb5bf00,
0xbd49bf00,0xbeff0000,0xbec6beb5,0xbea23eb5,0x3e153efb,0x3ef5bdc8,0x3ee23e8e,0x3e71bed5,0xbe71beed,0xbee23e44,0xbef5be44,0xbe153eed,0x3ea23ed5,0x3ec6be8e,0x3eff3dc8,0x3d49befb,
0x3dc83f00,0x3efb0000,0x3efb0000,0xbdc8bf00,0xbe8ebeed,0xbed53e44,0xbed53e44,0x3e8e3eed,0x3ed53eb5,0x3e8ebeb5,0x3e8ebeb5,0xbed5beb5,0xbefbbe44,0xbdc83eed,0xbdc83eed,0x3efb3e44,
0xbe15bf00,0xbef50000,0xbe713eb5,0x3ee23eb5,0x3ec63ed5,0x3ea2be8e,0xbd49befb,0xbeffbdc8,0xbeffbe44,0xbd493eed,0x3ea23eed,0x3ec6be44,0x3ee2bdc8,0xbe71befb,0xbef5be8e,0xbe153ed5,
0x3e443f00,0x3eed0000,0xbe44bf00,0xbeed0000,0xbeedbeb5,0xbe443eb5,0x3eed3eb5,0x3e44beb5,0x3eed0000,0xbe44bf00,0xbeed0000,0x3e443f00,0xbe443eb5,0x3eed3eb5,0x3e44beb5,0xbeedbeb5,
0xbe71bf00,0xbee20000,0x3ef53eb5,0x3e15beb5,0x3eff3e8e,0x3d49bed5,0xbec63dc8,0x3ea23efb,0xbea23e44,0x3ec63eed,0xbd49beed,0xbeffbe44,0xbe15befb,0xbef5bdc8,0x3ee23ed5,0x3e71be8e,
0x3e8e3f00,0x3ed50000,0xbed50000,0x3e8e3f00,0xbefbbe44,0x3dc83eed,0xbdc8beed,0xbefbbe44,0x3dc8beb5,0xbefbbeb5,0x3efb3eb5,0x3dc8beb5,0x3ed53eed,0x3e8ebe44,0xbe8e3e44,0x3ed53eed,
0xbea2bf00,0xbec60000,0x3d49beb5,0xbeffbeb5,0x3ee23dc8,0xbe71befb,0x3ef53ed5,0x3e15be8e,0x3e153eed,0x3ef53e44,0xbe713e44,0x3ee23eed,0xbeffbe8e,0x3d493ed5,0xbec6befb,0xbea23dc8,
0x3f003f00,0xbf003f00,0x3f003f00,0xbf003f00,0x3f003f00,0xbf003f00,0x3f003f00,0xbf003f00,0x3f003f00,0xbf003f00,0x3f003f00,0xbf003f00,0x3f003f00,0xbf003f00,0x3f003f00,0xbf003f00,
0x3d490000,0x3eff3f00,0x3ec63eb5,0x3ea23eb5,0x3e153dc8,0x3ef53efb,0x3ee23ed5,0x3e713e8e,0x3e713e44,0x3ee23eed,0x3ef53eed,0x3e153e44,0x3ea23e8e,0x3ec63ed5,0x3eff3efb,0x3d493dc8,
0xbefbbf00,0x3dc80000,0x3dc80000,0x3efb3f00,0xbed5beed,0x3e8e3e44,0x3e8e3e44,0x3ed53eed,0xbe8ebeb5,0x3ed53eb5,0x3ed53eb5,0x3e8e3eb5,0xbdc8be44,0x3efb3eed,0x3efb3eed,0x3dc83e44,
0xbe150000,0xbef5bf00,0xbe71beb5,0x3ee23eb5,0xbec6be8e,0xbea2bed5,0x3d49bdc8,0x3eff3efb,0xbeffbeed,0xbd49be44,0x3ea23e44,0x3ec63eed,0xbee2befb,0x3e713dc8,0x3ef53ed5,0x3e153e8e,
0x3eed3f00,0xbe440000,0xbeedbf00,0x3e440000,0x3e443eb5,0xbeedbeb5,0xbe44beb5,0x3eed3eb5,0xbe440000,0xbeedbf00,0x3e440000,0x3eed3f00,0xbeedbeb5,0xbe44beb5,0x3eed3eb5,0x3e443eb5,
0x3e710000,0x3ee23f00,0xbef5beb5,0xbe15beb5,0x3eff3ed5,0x3d493e8e,0xbec6befb,0x3ea23dc8,0x3ea23eed,0xbec6be44,0x3d49be44,0x3eff3eed,0xbe153dc8,0xbef5befb,0x3ee23e8e,0x3e713ed5,
0xbed5bf00,0x3e8e0000,0xbe8e0000,0xbed5bf00,0x3dc8be44,0x3efb3eed,0xbefbbeed,0x3dc8be44,0x3efb3eb5,0x3dc83eb5,0xbdc8beb5,0x3efb3eb5,0x3e8e3eed,0xbed5be44,0x3ed53e44,0x3e8e3eed,
0xbea20000,0xbec6bf00,0x3d493eb5,0xbeffbeb5,0xbee2befb,0x3e71bdc8,0xbef5be8e,0xbe15bed5,0x3e15be44,0x3ef53eed,0xbe71beed,0x3ee23e44,0x3eff3ed5,0xbd493e8e,0x3ec63dc8,0x3ea23efb,
0x3f00,0xbf000000,0x3f00,0xbf000000,0xbf00,0x3f000000,0xbf00,0x3f000000,0x3f00,0xbf000000,0x3f00,0xbf000000,0xbf00,0x3f000000,0xbf00,0x3f000000,
0x3eff0000,0xbd493f00,0x3ea23eb5,0xbec63eb5,0xbef5bdc8,0x3e15befb,0xbe71bed5,0x3ee2be8e,0x3ee23e44,0xbe713eed,0x3e153eed,0xbef53e44,0xbec6be8e,0x3ea2bed5,0xbd49befb,0x3effbdc8,
0x3dc8bf00,0x3efb0000,0x3efb0000,0xbdc83f00,0xbe8e3eed,0xbed5be44,0xbed5be44,0x3e8ebeed,0x3ed5beb5,0x3e8e3eb5,0x3e8e3eb5,0xbed53eb5,0xbefb3e44,0xbdc8beed,0xbdc8beed,0x3efbbe44,
0xbef50000,0x3e15bf00,0x3ee2beb5,0x3e713eb5,0x3ea23e8e,0xbec63ed5,0xbeff3dc8,0x3d49befb,0xbd49beed,0x3effbe44,0x3ec63e44,0xbea23eed,0xbe713efb,0xbee2bdc8,0xbe15bed5,0x3ef5be8e,
0xbe443f00,0xbeed0000,0x3e44bf00,0x3eed0000,0x3eedbeb5,0x3e443eb5,0xbeed3eb5,0xbe44beb5,0xbeed0000,0x3e44bf00,0x3eed0000,0xbe443f00,0x3e443eb5,0xbeed3eb5,0xbe44beb5,0x3eedbeb5,
0x3ee20000,0xbe713f00,0xbe15beb5,0x3ef5beb5,0xbd49bed5,0x3effbe8e,0xbea23efb,0xbec6bdc8,0xbec63eed,0xbea2be44,0x3effbe44,0xbd493eed,0x3ef5bdc8,0xbe153efb,0xbe71be8e,0x3ee2bed5,
0x3e8ebf00,0x3ed50000,0xbed50000,0x3e8ebf00,0xbefb3e44,0x3dc8beed,0xbdc83eed,0xbefb3e44,0x3dc83eb5,0xbefb3eb5,0x3efbbeb5,0x3dc83eb5,0x3ed5beed,0x3e8e3e44,0xbe8ebe44,0x3ed5beed,
0xbec60000,0x3ea2bf00,0xbeff3eb5,0xbd49beb5,0xbe713efb,0xbee23dc8,0x3e153e8e,0xbef53ed5,0x3ef5be44,0xbe153eed,0x3ee2beed,0x3e713e44,0x3d49bed5,0x3effbe8e,0xbea2bdc8,0x3ec6befb,
0x3eb53f00,0xbeb50000,0x3eb53f00,0xbeb50000,0xbeb50000,0xbeb5bf00,0xbeb50000,0xbeb5bf00,0xbeb5bf00,0x3eb50000,0xbeb5bf00,0x3eb50000,0x3eb50000,0x3eb53f00,0x3eb50000,0x3eb53f00,
0xbd490000,0xbeff3f00,0xbec63eb5,0xbea23eb5,0xbe153dc8,0xbef53efb,0xbee23ed5,0xbe713e8e,0xbe713e44,0xbee23eed,0xbef53eed,0xbe153e44,0xbea23e8e,0xbec63ed5,0xbeff3efb,0xbd493dc8,
0x3efbbf00,0xbdc80000,0xbdc80000,0xbefb3f00,0x3ed5beed,0xbe8e3e44,0xbe8e3e44,0xbed53eed,0x3e8ebeb5,0xbed53eb5,0xbed53eb5,0xbe8e3eb5,0x3dc8be44,0xbefb3eed,0xbefb3eed,0xbdc83e44,
0x3e150000,0x3ef5bf00,0x3e71beb5,0xbee23eb5,0x3ec6be8e,0x3ea2bed5,0xbd49bdc8,0xbeff3efb,0x3effbeed,0x3d49be44,0xbea23e44,0xbec63eed,0x3ee2befb,0xbe713dc8,0xbef53ed5,0xbe153e8e,
0xbeed3f00,0x3e440000,0x3eedbf00,0xbe440000,0xbe443eb5,0x3eedbeb5,0x3e44beb5,0xbeed3eb5,0x3e440000,0x3eedbf00,0xbe440000,0xbeed3f00,0x3eedbeb5,0x3e44beb5,0xbeed3eb5,0xbe443eb5,
0xbe710000,0xbee23f00,0x3ef5beb5,0x3e15beb5,0xbeff3ed5,0xbd493e8e,0x3ec6befb,0xbea23dc8,0xbea23eed,0x3ec6be44,0xbd49be44,0xbeff3eed,0x3e153dc8,0x3ef5befb,0xbee23e8e,0xbe713ed5,
0x3ed5bf00,0xbe8e0000,0x3e8e0000,0x3ed5bf00,0xbdc8be44,0xbefb3eed,0x3efbbeed,0xbdc8be44,0xbefb3eb5,0xbdc83eb5,0x3dc8beb5,0xbefb3eb5,0xbe8e3eed,0x3ed5be44,0xbed53e44,0xbe8e3eed,
0x3ea20000,0x3ec6bf00,0xbd493eb5,0x3effbeb5,0x3ee2befb,0xbe71bdc8,0x3ef5be8e,0x3e15bed5,0xbe15be44,0xbef53eed,0x3e71beed,0xbee23e44,0xbeff3ed5,0x3d493e8e,0xbec63dc8,0xbea23efb,
0xbeb53f00,0xbeb50000,0xbeb53f00,0xbeb50000,0x3eb50000,0xbeb53f00,0x3eb50000,0xbeb53f00,0x3eb5bf00,0x3eb50000,0x3eb5bf00,0x3eb50000,0xbeb50000,0x3eb5bf00,0xbeb50000,0x3eb5bf00,
0xbeff0000,0x3d493f00,0xbea23eb5,0x3ec63eb5,0x3ef5bdc8,0xbe15befb,0x3e71bed5,0xbee2be8e,0xbee23e44,0x3e713eed,0xbe153eed,0x3ef53e44,0x3ec6be8e,0xbea2bed5,0x3d49befb,0xbeffbdc8,
0xbdc8bf00,0xbefb0000,0xbefb0000,0x3dc83f00,0x3e8e3eed,0x3ed5be44,0x3ed5be44,0xbe8ebeed,0xbed5beb5,0xbe8e3eb5,0xbe8e3eb5,0x3ed53eb5,0x3efb3e44,0x3dc8beed,0x3dc8beed,0xbefbbe44,
0x3ef50000,0xbe15bf00,0xbee2beb5,0xbe713eb5,0xbea23e8e,0x3ec63ed5,0x3eff3dc8,0xbd49befb,0x3d49beed,0xbeffbe44,0xbec63e44,0x3ea23eed,0x3e713efb,0x3ee2bdc8,0x3e15bed5,0xbef5be8e,
0x3e443f00,0x3eed0000,0xbe44bf00,0xbeed0000,0xbeedbeb5,0xbe443eb5,0x3eed3eb5,0x3e44beb5,0x3eed0000,0xbe44bf00,0xbeed0000,0x3e443f00,0xbe443eb5,0x3eed3eb5,0x3e44beb5,0xbeedbeb5,
0xbee20000,0x3e713f00,0x3e15beb5,0xbef5beb5,0x3d49bed5,0xbeffbe8e,0x3ea23efb,0x3ec6bdc8,0x3ec63eed,0x3ea2be44,0xbeffbe44,0x3d493eed,0xbef5bdc8,0x3e153efb,0x3e71be8e,0xbee2bed5,
0xbe8ebf00,0xbed50000,0x3ed50000,0xbe8ebf00,0x3efb3e44,0xbdc8beed,0x3dc83eed,0x3efb3e44,0xbdc83eb5,0x3efb3eb5,0xbefbbeb5,0xbdc83eb5,0xbed5beed,0xbe8e3e44,0x3e8ebe44,0xbed5beed,
0x3ec60000,0xbea2bf00,0x3eff3eb5,0x3d49beb5,0x3e713efb,0x3ee23dc8,0xbe153e8e,0x3ef53ed5,0xbef5be44,0x3e153eed,0xbee2beed,0xbe713e44,0xbd49bed5,0xbeffbe8e,0x3ea2bdc8,0xbec6befb,
0x3f800000,0x0,0x3f800000,0x0,0x3f800000,0x0,0x3f800000,0x0,0x3f800000,0x0,0x3f800000,0x0,0x3f800000,0x0,0x3f800000,0x0,
0x3f800000,0x0,0x3f7fec43,0xbcc90ab0,0x3f7fb10f,0xbd48fb30,0x3f7f4e6d,0xbd96a905,0x3f7ec46d,0xbdc8bd36,0x3f7e1324,0xbdfab273,0x3f7d3aac,0xbe164083,0x3f7c3b28,0xbe2f10a2,
0x3f800000,0x0,0x3f7ffec4,0xbbc90f88,0x3f7ffb11,0xbc490e90,0x3f7ff4e6,0xbc96c9b6,0x3f7fec43,0xbcc90ab0,0x3f7fe129,0xbcfb49ba,0x3f7fd397,0xbd16c32c,0x3f7fc38f,0xbd2fe007,
0x3f800000,0x0,0x3f7fe129,0xbcfb49ba,0x3f7f84ab,0xbd7b2b74,0x3f7eea9d,0xbdbc3ac3,0x3f7e1324,0xbdfab273,0x3f7cfe73,0xbe1c76de,0x3f7baccd,0xbe3b6ecf,0x3f7a1e84,0xbe5a3997,
0x3f800000,0x0,0x3f7ffb11,0xbc490e90,0x3f7fec43,0xbcc90ab0,0x3f7fd397,0xbd16c32c,0x3f7fb10f,0xbd48fb30,0x3f7f84ab,0xbd7b2b74,0x3f7f4e6d,0xbd96a905,0x3f7f0e58,0xbdafb680,
0x3f800000,0x0,0x3f7fd397,0xbd16c32c,0x3f7f4e6d,0xbd96a905,0x3f7e70b0,0xbde1bc2e,0x3f7d3aac,0xbe164083,0x3f7baccd,0xbe3b6ecf,0x3f79c79d,0xbe605c13,0x3f778bc5,0xbe827dc0,
0x3f800000,0x0,0x3f7ff4e6,0xbc96c9b6,0x3f7fd397,0xbd16c32c,0x3f7f9c18,0xbd621469,0x3f7f4e6d,0xbd96a905,0x3f7eea9d,0xbdbc3ac3,0x3f7e70b0,0xbde1bc2e,0x3f7de0b1,0xbe039502,
0x3f800000,0x0,0x3f7fc38f,0xbd2fe007,0x3f7f0e58,0xbdafb680,0x3f7de0b1,0xbe039502,0x3f7c3b28,0xbe2f10a2,0x3f7a1e84,0xbe5a3997,0x3f778bc5,0xbe827dc0,0x3f748422,0xbe97a117,
0x3f800000,0x0,0x3f7fb10f,0xbd48fb30,0x3f7ec46d,0xbdc8bd36,0x3f7d3aac,0xbe164083,0x3f7b14be,0xbe47c5c2,0x3f7853f8,0xbe78cfcc,0x3f74fa0b,0xbe94a031,0x3f710908,0xbeac7cd4,
0x3f800000,0x0,0x3f7f4e6d,0xbd96a905,0x3f7d3aac,0xbe164083,0x3f79c79d,0xbe605c13,0x3f74fa0b,0xbe94a031,0x3f6ed89e,0xbeb8442a,0x3f676bd8,0xbedae880,0x3f5ebe05,0xbefc5d27,
0x3f800000,0x0,0x3f7f9c18,0xbd621469,0x3f7e70b0,0xbde1bc2e,0x3f7c7eb0,0xbe28defc,0x3f79c79d,0xbe605c13,0x3f764d97,0xbe8b9507,0x3f721352,0xbea68f12,0x3f6d1c1d,0xbec1071e,
0x3f800000,0x0,0x3f7f2f9d,0xbda3308c,0x3f7cbfc9,0xbe22abb6,0x3f78b47b,0xbe72b651,0x3f731447,0xbea09ae5,0x3f6be858,0xbec6d529,0x3f633c5a,0xbeebcbbb,0x3f591e6a,0xbf07a136,
0x3f800000,0x0,0x3f7f84ab,0xbd7b2b74,0x3f7e1324,0xbdfab273,0x3f7baccd,0xbe3b6ecf,0x3f7853f8,0xbe78cfcc,0x3f740bdd,0xbe9aa086,0x3f6ed89e,0xbeb8442a,0x3f68bf3c,0xbed53641,
0x3f800000,0x0,0x3f7f0e58,0xbdafb680,0x3f7c3b28,0xbe2f10a2,0x3f778bc5,0xbe827dc0,0x3f710908,0xbeac7cd4,0x3f68bf3c,0xbed53641,0x3f5ebe05,0xbefc5d27,0x3f531849,0xbf10d3cd,
0x3f800000,0x0,0x3f7f6ac7,0xbd8a200a,0x3f7dabcc,0xbe09cf86,0x3f7ac516,0xbe4dee60,0x3f76ba07,0xbe888e93,0x3f718f57,0xbea986c4,0x3f6b4b0c,0xbec9b953,0x3f63f473,0xbee900b7,
0x3f800000,0x0,0x3f7eea9d,0xbdbc3ac3,0x3f7baccd,0xbe3b6ecf,0x3f764d97,0xbe8b9507,0x3f6ed89e,0xbeb8442a,0x3f655e0b,0xbee363fa,0x3f59f26a,0xbf064b82,0x3f4cae79,0xbf19c200,
0x3f800000,0x0,0x3f7ec46d,0xbdc8bd36,0x3f7b14be,0xbe47c5c2,0x3f74fa0b,0xbe94a031,0x3f6c835e,0xbec3ef15,0x3f61c598,0xbef15aea,0x3f54db31,0xbf0e39da,0x3f45e403,0xbf226799,
0x3f800000,0x0,0x3f7e1324,0xbdfab273,0x3f7853f8,0xbe78cfcc,0x3f6ed89e,0xbeb8442a,0x3f61c598,0xbef15aea,0x3f514d3d,0xbf13682a,0x3f3daef9,0xbf2beb4a,0x3f273656,0xbf41d870,
0x3f800000,0x0,0x3f7e9bc9,0xbdd53db9,0x3f7a7302,0xbe541501,0x3f73913f,0xbe9d9e78,0x3f6a09a7,0xbecf7bca,0x3f5df6be,0xbeff17b2,0x3f4f7a1f,0xbf15f6d9,0x3f3ebc1b,0xbf2ac082,
0x3f800000,0x0,0x3f7de0b1,0xbe039502,0x3f778bc5,0xbe827dc0,0x3f6d1c1d,0xbec1071e,0x3f5ebe05,0xbefc5d27,0x3f4cae79,0xbf19c200,0x3f373a23,0xbf32c8c9,0x3f1ebc12,0xbf48d8b3,
0x3f800000,0x0,0x3f7e70b0,0xbde1bc2e,0x3f79c79d,0xbe605c13,0x3f721352,0xbea68f12,0x3f676bd8,0xbedae880,0x3f59f26a,0xbf064b82,0x3f49d112,0xbf1d7fd1,0x3f373a23,0xbf32c8c9,
0x3f800000,0x0,0x3f7dabcc,0xbe09cf86,0x3f76ba07,0xbe888e93,0x3f6b4b0c,0xbec9b953,0x3f5b941a,0xbf039c3d,0x3f47de65,0xbf1ff6cb,0x3f3085bb,0xbf396842,0x3f15f6d9,0xbf4f7a1f,
0x3f800000,0x0,0x3f7e4323,0xbdee3876,0x3f791298,0xbe6c9a7f,0x3f708066,0xbeaf713a,0x3f64aa59,0xbee63375,0x3f55b993,0xbf0cead0,0x3f43e200,0xbf24d225,0x3f2f61a5,0xbf3a7ca4,
0x3f800000,0x0,0x3f7d7474,0xbe1008b7,0x3f75dec6,0xbe8e9a22,0x3f696591,0xbed25a09,0x3f584853,0xbf08f59b,0x3f42de29,0xbf26050a,0x3f299415,0xbf3fc767,0x3f0cead0,0xbf55b993,
0x3f800000,0x0,0x3f7d3aac,0xbe164083,0x3f74fa0b,0xbe94a031,0x3f676bd8,0xbedae880,0x3f54db31,0xbf0e39da,0x3f3daef9,0xbf2beb4a,0x3f226799,0xbf45e403,0x3f039c3d,0xbf5b941a,
0x3f800000,0x0,0x3f7c3b28,0xbe2f10a2,0x3f710908,0xbeac7cd4,0x3f5ebe05,0xbefc5d27,0x3f45e403,0xbf226799,0x3f273656,0xbf41d870,0x3f039c3d,0xbf5b941a,0x3eb8442a,0xbf6ed89e,
0x3f800000,0x0,0x3f7cfe73,0xbe1c76de,0x3f740bdd,0xbe9aa086,0x3f655e0b,0xbee363fa,0x3f514d3d,0xbf13682a,0x3f385216,0xbf31a81d,0x3f1b02c6,0xbf4bbbf8,0x3ef41f07,0xbf6106f2,
0x3f800000,0x0,0x3f7bf531,0xbe354098,0x3f6ff573,0xbeb263ef,0x3f5c61c7,0xbf0242b1,0x3f41d870,0xbf273656,0x3f212ff9,0xbf46e22a,0x3ef6e0cb,0xbf604621,0x3ea395c5,0xbf7294f8,
0x3f800000,0x0,0x3f7cbfc9,0xbe22abb6,0x3f731447,0xbea09ae5,0x3f633c5a,0xbeebcbbb,0x3f4d9f02,0xbf187fc0,0x3f32c8c9,0xbf373a23,0x3f13682a,0xbf514d3d,0x3ee0924f,0xbf660f88,
0x3f800000,0x0,0x3f7baccd,0xbe3b6ecf,0x3f6ed89e,0xbeb8442a,0x3f59f26a,0xbf064b82,0x3f3daef9,0xbf2beb4a,0x3f1b02c6,0xbf4bbbf8,0x3ee63375,0xbf64aa59,0x3e8e9a22,0xbf75dec6,
0x3f800000,0x0,0x3f7c7eb0,0xbe28defc,0x3f721352,0xbea68f12,0x3f6106f2,0xbef41f07,0x3f49d112,0xbf1d7fd1,0x3f2d1469,0xbf3ca003,0x3f0b9a6b,0xbf5695e5,0x3ecc9b8b,0xbf6aab7b,
0x3f800000,0x0,0x3f7b61fc,0xbe419b37,0x3f6db293,0xbebe1d4a,0x3f577026,0xbf0a48ad,0x3f396842,0xbf3085bb,0x3f14b039,0xbf5064af,0x3ed53641,0xbf68bf3c,0x3e72b651,0xbf78b47b,
0x3f800000,0x0,0x3f800000,0x0,0x3f800000,0x0,0x3f800000,0x0,0x3f800000,0x0,0x3f800000,0x0,0x3f800000,0x0,0x3f800000,0x0,
0x3f7b14be,0xbe47c5c2,0x3f79c79d,0xbe605c13,0x3f7853f8,0xbe78cfcc,0x3f76ba07,0xbe888e93,0x3f74fa0b,0xbe94a031,0x3f731447,0xbea09ae5,0x3f710908,0xbeac7cd4,0x3f6ed89e,0xbeb8442a,
0x3f7fb10f,0xbd48fb30,0x3f7f9c18,0xbd621469,0x3f7f84ab,0xbd7b2b74,0x3f7f6ac7,0xbd8a200a,0x3f7f4e6d,0xbd96a905,0x3f7f2f9d,0xbda3308c,0x3f7f0e58,0xbdafb680,0x3f7eea9d,0xbdbc3ac3,
0x3f7853f8,0xbe78cfcc,0x3f764d97,0xbe8b9507,0x3f740bdd,0xbe9aa086,0x3f718f57,0xbea986c4,0x3f6ed89e,0xbeb8442a,0x3f6be858,0xbec6d529,0x3f68bf3c,0xbed53641,0x3f655e0b,0xbee363fa,
0x3f7ec46d,0xbdc8bd36,0x3f7e70b0,0xbde1bc2e,0x3f7e1324,0xbdfab273,0x3f7dabcc,0xbe09cf86,0x3f7d3aac,0xbe164083,0x3f7cbfc9,0xbe22abb6,0x3f7c3b28,0xbe2f10a2,0x3f7baccd,0xbe3b6ecf,
0x3f74fa0b,0xbe94a031,0x3f721352,0xbea68f12,0x3f6ed89e,0xbeb8442a,0x3f6b4b0c,0xbec9b953,0x3f676bd8,0xbedae880,0x3f633c5a,0xbeebcbbb,0x3f5ebe05,0xbefc5d27,0x3f59f26a,0xbf064b82,
0x3f7d3aac,0xbe164083,0x3f7c7eb0,0xbe28defc,0x3f7baccd,0xbe3b6ecf,0x3f7ac516,0xbe4dee60,0x3f79c79d,0xbe605c13,0x3f78b47b,0xbe72b651,0x3f778bc5,0xbe827dc0,0x3f764d97,0xbe8b9507,
0x3f710908,0xbeac7cd4,0x3f6d1c1d,0xbec1071e,0x3f68bf3c,0xbed53641,0x3f63f473,0xbee900b7,0x3f5ebe05,0xbefc5d27,0x3f591e6a,0xbf07a136,0x3f531849,0xbf10d3cd,0x3f4cae79,0xbf19c200,
0x3f6c835e,0xbec3ef15,0x3f676bd8,0xbedae880,0x3f61c598,0xbef15aea,0x3f5b941a,0xbf039c3d,0x3f54db31,0xbf0e39da,0x3f4d9f02,0xbf187fc0,0x3f45e403,0xbf226799,0x3f3daef9,0xbf2beb4a,
0x3f54db31,0xbf0e39da,0x3f49d112,0xbf1d7fd1,0x3f3daef9,0xbf2beb4a,0x3f3085bb,0xbf396842,0x3f226799,0xbf45e403,0x3f13682a,0xbf514d3d,0x3f039c3d,0xbf5b941a,0x3ee63375,0xbf64aa59,
0x3f676bd8,0xbedae880,0x3f6106f2,0xbef41f07,0x3f59f26a,0xbf064b82,0x3f5233c6,0xbf121eb0,0x3f49d112,0xbf1d7fd1,0x3f40d0da,0xbf286605,0x3f373a23,0xbf32c8c9,0x3f2d1469,0xbf3ca003,
0x3f4d9f02,0xbf187fc0,0x3f40d0da,0xbf286605,0x3f32c8c9,0xbf373a23,0x3f239da9,0xbf44e3f5,0x3f13682a,0xbf514d3d,0x3f0242b1,0xbf5c61c7,0x3ee0924f,0xbf660f88,0x3ebb31a0,0xbf6e46be,
0x3f61c598,0xbef15aea,0x3f59f26a,0xbf064b82,0x3f514d3d,0xbf13682a,0x3f47de65,0xbf1ff6cb,0x3f3daef9,0xbf2beb4a,0x3f32c8c9,0xbf373a23,0x3f273656,0xbf41d870,0x3f1b02c6,0xbf4bbbf8,
0x3f45e403,0xbf226799,0x3f373a23,0xbf32c8c9,0x3f273656,0xbf41d870,0x3f15f6d9,0xbf4f7a1f,0x3f039c3d,0xbf5b941a,0x3ee0924f,0xbf660f88,0x3eb8442a,0xbf6ed89e,0x3e8e9a22,0xbf75dec6,
0x3f5b941a,0xbf039c3d,0x3f5233c6,0xbf121eb0,0x3f47de65,0xbf1ff6cb,0x3f3ca003,0xbf2d1469,0x3f3085bb,0xbf396842,0x3f239da9,0xbf44e3f5,0x3f15f6d9,0xbf4f7a1f,0x3f07a136,0xbf591e6a,
0x3f3daef9,0xbf2beb4a,0x3f2d1469,0xbf3ca003,0x3f1b02c6,0xbf4bbbf8,0x3f07a136,0xbf591e6a,0x3ee63375,0xbf64aa59,0x3ebb31a0,0xbf6e46be,0x3e8e9a22,0xbf75dec6,0x3e419b37,0xbf7b61fc,
0x3f3504f3,0xbf3504f3,0x3f226799,0xbf45e403,0x3f0e39da,0xbf54db31,0x3ef15aea,0xbf61c598,0x3ec3ef15,0xbf6c835e,0x3e94a031,0xbf74fa0b,0x3e47c5c2,0xbf7b14be,0x3dc8bd36,0xbf7ec46d,
0x3f0e39da,0xbf54db31,0x3ee63375,0xbf64aa59,0x3eac7cd4,0xbf710908,0x3e605c13,0xbf79c79d,0x3dc8bd36,0xbf7ec46d,0xbcc90ab0,0xbf7fec43,0xbe164083,0xbf7d3aac,0xbe888e93,0xbf76ba07,
0x3f2beb4a,0xbf3daef9,0x3f173c07,0xbf4e8d90,0x3f00e7e4,0xbf5d2d53,0x3ed25a09,0xbf696591,0x3ea09ae5,0xbf731447,0x3e5a3997,0xbf7a1e84,0x3de1bc2e,0xbf7e70b0,0x3bc90f88,0xbf7ffec4,
0x3f039c3d,0xbf5b941a,0x3ecc9b8b,0xbf6aab7b,0x3e8e9a22,0xbf75dec6,0x3e1c76de,0xbf7cfe73,0x3cc90ab0,0xbf7fec43,0xbdd53db9,0xbf7e9bc9,0xbe6c9a7f,0xbf791298,0xbeb554ec,0xbf6f6830,
0x3f226799,0xbf45e403,0x3f0b9a6b,0xbf5695e5,0x3ee63375,0xbf64aa59,0x3eb263ef,0xbf6ff573,0x3e78cfcc,0xbf7853f8,0x3e09cf86,0xbf7dabcc,0x3cc90ab0,0xbf7fec43,0xbdafb680,0xbf7f0e58,
0x3ef15aea,0xbf61c598,0x3eb263ef,0xbf6ff573,0x3e605c13,0xbf79c79d,0x3dafb680,0xbf7f0e58,0xbd48fb30,0xbf7fb10f,0xbe3b6ecf,0xbf7baccd,0xbea09ae5,0xbf731447,0xbee0924f,0xbf660f88,
0x3f187fc0,0xbf4d9f02,0x3eff17b2,0xbf5df6be,0x3ec9b953,0xbf6b4b0c,0x3e919ddd,0xbf756d97,0x3e2f10a2,0xbf7c3b28,0x3d621469,0xbf7f9c18,0xbd7b2b74,0xbf7f84ab,0xbe354098,0xbf7bf531,
0x3edae880,0xbf676bd8,0x3e97a117,0xbf748422,0x3e22abb6,0xbf7cbfc9,0x3c96c9b6,0xbf7ff4e6,0xbdfab273,0xbf7e1324,0xbe8586ce,0xbf772417,0xbec9b953,0xbf6b4b0c,0xbf04f484,0xbf5ac450,
0x3ec3ef15,0xbf6c835e,0x3e78cfcc,0xbf7853f8,0x3dc8bd36,0xbf7ec46d,0xbd48fb30,0xbf7fb10f,0xbe47c5c2,0xbf7b14be,0xbeac7cd4,0xbf710908,0xbef15aea,0xbf61c598,0xbf187fc0,0xbf4d9f02,
0x3e47c5c2,0xbf7b14be,0x3cc90ab0,0xbf7fec43,0xbe164083,0xbf7d3aac,0xbea09ae5,0xbf731447,0xbef15aea,0xbf61c598,0xbf1d7fd1,0xbf49d112,0xbf3daef9,0xbf2beb4a,0xbf584853,0xbf08f59b,
0x3eac7cd4,0xbf710908,0x3e419b37,0xbf7b61fc,0x3d16c32c,0xbf7fd397,0xbdee3876,0xbf7e4323,0xbe888e93,0xbf76ba07,0xbed25a09,0xbf696591,0xbf0b9a6b,0xbf5695e5,0xbf2ac082,0xbf3ebc1b,
0x3e164083,0xbf7d3aac,0xbcfb49ba,0xbf7fe129,0xbe541501,0xbf7a7302,0xbec1071e,0xbf6d1c1d,0xbf08f59b,0xbf584853,0xbf2d1469,0xbf3ca003,0xbf4bbbf8,0xbf1b02c6,0xbf63f473,0xbee900b7,
0x3e94a031,0xbf74fa0b,0x3e09cf86,0xbf7dabcc,0xbcc90ab0,0xbf7fec43,0xbe3b6ecf,0xbf7baccd,0xbeac7cd4,0xbf710908,0xbef6e0cb,0xbf604621,0xbf1d7fd1,0xbf49d112,0xbf3b8f3b,0xbf2e3bde,
0x3dc8bd36,0xbf7ec46d,0xbdafb680,0xbf7f0e58,0xbe888e93,0xbf76ba07,0xbee0924f,0xbf660f88,0xbf187fc0,0xbf4d9f02,0xbf3b8f3b,0xbf2e3bde,0xbf584853,0xbf08f59b,0xbf6db293,0xbebe1d4a,
0x3e78cfcc,0xbf7853f8,0x3da3308c,0xbf7f2f9d,0xbdafb680,0xbf7f0e58,0xbe7ee6e1,0xbf77f110,0xbecf7bca,0xbf6a09a7,0xbf0cead0,0xbf55b993,0xbf2e3bde,0xbf3b8f3b,0xbf4ac77f,0xbf1c420c,
0x3d48fb30,0xbf7fb10f,0xbe1008b7,0xbf7d7474,0xbea68f12,0xbf721352,0xbeff17b2,0xbf5df6be,0xbf273656,0xbf41d870,0xbf48d8b3,0xbf1ebc12,0xbf633c5a,0xbeebcbbb,0xbf756d97,0xbe919ddd,
0x3f800000,0x0,0x3f800000,0x0,0x3f800000,0x0,0x3f800000,0x0,0x3f800000,0x0,0x3f800000,0x0,0x3f800000,0x0,0x3f800000,0x0,
0x3f6c835e,0xbec3ef15,0x3f6a09a7,0xbecf7bca,0x3f676bd8,0xbedae880,0x3f64aa59,0xbee63375,0x3f61c598,0xbef15aea,0x3f5ebe05,0xbefc5d27,0x3f5b941a,0xbf039c3d,0x3f584853,0xbf08f59b,
0x3f7ec46d,0xbdc8bd36,0x3f7e9bc9,0xbdd53db9,0x3f7e70b0,0xbde1bc2e,0x3f7e4323,0xbdee3876,0x3f7e1324,0xbdfab273,0x3f7de0b1,0xbe039502,0x3f7dabcc,0xbe09cf86,0x3f7d7474,0xbe1008b7,
0x3f61c598,0xbef15aea,0x3f5df6be,0xbeff17b2,0x3f59f26a,0xbf064b82,0x3f55b993,0xbf0cead0,0x3f514d3d,0xbf13682a,0x3f4cae79,0xbf19c200,0x3f47de65,0xbf1ff6cb,0x3f42de29,0xbf26050a,
0x3f7b14be,0xbe47c5c2,0x3f7a7302,0xbe541501,0x3f79c79d,0xbe605c13,0x3f791298,0xbe6c9a7f,0x3f7853f8,0xbe78cfcc,0x3f778bc5,0xbe827dc0,0x3f76ba07,0xbe888e93,0x3f75dec6,0xbe8e9a22,
0x3f54db31,0xbf0e39da,0x3f4f7a1f,0xbf15f6d9,0x3f49d112,0xbf1d7fd1,0x3f43e200,0xbf24d225,0x3f3daef9,0xbf2beb4a,0x3f373a23,0xbf32c8c9,0x3f3085bb,0xbf396842,0x3f299415,0xbf3fc767,
0x3f74fa0b,0xbe94a031,0x3f73913f,0xbe9d9e78,0x3f721352,0xbea68f12,0x3f708066,0xbeaf713a,0x3f6ed89e,0xbeb8442a,0x3f6d1c1d,0xbec1071e,0x3f6b4b0c,0xbec9b953,0x3f696591,0xbed25a09,
0x3f45e403,0xbf226799,0x3f3ebc1b,0xbf2ac082,0x3f373a23,0xbf32c8c9,0x3f2f61a5,0xbf3a7ca4,0x3f273656,0xbf41d870,0x3f1ebc12,0xbf48d8b3,0x3f15f6d9,0xbf4f7a1f,0x3f0cead0,0xbf55b993,
0x3f3504f3,0xbf3504f3,0x3f2beb4a,0xbf3daef9,0x3f226799,0xbf45e403,0x3f187fc0,0xbf4d9f02,0x3f0e39da,0xbf54db31,0x3f039c3d,0xbf5b941a,0x3ef15aea,0xbf61c598,0x3edae880,0xbf676bd8,
0x3ec3ef15,0xbf6c835e,0x3ea09ae5,0xbf731447,0x3e78cfcc,0xbf7853f8,0x3e2f10a2,0xbf7c3b28,0x3dc8bd36,0xbf7ec46d,0x3cc90ab0,0xbf7fec43,0xbd48fb30,0xbf7fb10f,0xbdfab273,0xbf7e1324,
0x3f226799,0xbf45e403,0x3f173c07,0xbf4e8d90,0x3f0b9a6b,0xbf5695e5,0x3eff17b2,0xbf5df6be,0x3ee63375,0xbf64aa59,0x3ecc9b8b,0xbf6aab7b,0x3eb263ef,0xbf6ff573,0x3e97a117,0xbf748422,
0x3e94a031,0xbf74fa0b,0x3e5a3997,0xbf7a1e84,0x3e09cf86,0xbf7dabcc,0x3d621469,0xbf7f9c18,0xbcc90ab0,0xbf7fec43,0xbdd53db9,0xbf7e9bc9,0xbe3b6ecf,0xbf7baccd,0xbe8586ce,0xbf772417,
0x3f0e39da,0xbf54db31,0x3f00e7e4,0xbf5d2d53,0x3ee63375,0xbf64aa59,0x3ec9b953,0xbf6b4b0c,0x3eac7cd4,0xbf710908,0x3e8e9a22,0xbf75dec6,0x3e605c13,0xbf79c79d,0x3e22abb6,0xbf7cbfc9,
0x3e47c5c2,0xbf7b14be,0x3de1bc2e,0xbf7e70b0,0x3cc90ab0,0xbf7fec43,0xbd7b2b74,0xbf7f84ab,0xbe164083,0xbf7d3aac,0xbe6c9a7f,0xbf791298,0xbea09ae5,0xbf731447,0xbec9b953,0xbf6b4b0c,
0x3ef15aea,0xbf61c598,0x3ed25a09,0xbf696591,0x3eb263ef,0xbf6ff573,0x3e919ddd,0xbf756d97,0x3e605c13,0xbf79c79d,0x3e1c76de,0xbf7cfe73,0x3dafb680,0xbf7f0e58,0x3c96c9b6,0xbf7ff4e6,
0x3dc8bd36,0xbf7ec46d,0x3bc90f88,0xbf7ffec4,0xbdafb680,0xbf7f0e58,0xbe354098,0xbf7bf531,0xbe888e93,0xbf76ba07,0xbeb554ec,0xbf6f6830,0xbee0924f,0xbf660f88,0xbf04f484,0xbf5ac450,
0x0,0xbf800000,0xbdc8bd36,0xbf7ec46d,0xbe47c5c2,0xbf7b14be,0xbe94a031,0xbf74fa0b,0xbec3ef15,0xbf6c835e,0xbef15aea,0xbf61c598,0xbf0e39da,0xbf54db31,0xbf226799,0xbf45e403,
0xbec3ef15,0xbf6c835e,0xbefc5d27,0xbf5ebe05,0xbf187fc0,0xbf4d9f02,0xbf3085bb,0xbf396842,0xbf45e403,0xbf226799,0xbf584853,0xbf08f59b,0xbf676bd8,0xbedae880,0xbf731447,0xbea09ae5,
0xbdc8bd36,0xbf7ec46d,0xbe4dee60,0xbf7ac516,0xbe9aa086,0xbf740bdd,0xbecc9b8b,0xbf6aab7b,0xbefc5d27,0xbf5ebe05,0xbf14b039,0xbf5064af,0xbf299415,0xbf3fc767,0xbf3ca003,0xbf2d1469,
0xbef15aea,0xbf61c598,0xbf14b039,0xbf5064af,0xbf2e3bde,0xbf3b8f3b,0xbf44e3f5,0xbf239da9,0xbf584853,0xbf08f59b,0xbf6816a8,0xbed8106b,0xbf740bdd,0xbe9aa086,0xbf7bf531,0xbe354098,
0xbe47c5c2,0xbf7b14be,0xbe9aa086,0xbf740bdd,0xbecf7bca,0xbf6a09a7,0xbf00e7e4,0xbf5d2d53,0xbf187fc0,0xbf4d9f02,0xbf2e3bde,0xbf3b8f3b,0xbf41d870,0xbf273656,0xbf531849,0xbf10d3cd,
0xbf0e39da,0xbf54db31,0xbf299415,0xbf3fc767,0xbf41d870,0xbf273656,0xbf5695e5,0xbf0b9a6b,0xbf676bd8,0xbedae880,0xbf740bdd,0xbe9aa086,0xbf7c3b28,0xbe2f10a2,0xbf7fd397,0xbd16c32c,
0xbe94a031,0xbf74fa0b,0xbecc9b8b,0xbf6aab7b,0xbf00e7e4,0xbf5d2d53,0xbf19c200,0xbf4cae79,0xbf3085bb,0xbf396842,0xbf44e3f5,0xbf239da9,0xbf5695e5,0xbf0b9a6b,0xbf655e0b,0xbee363fa,
0xbf226799,0xbf45e403,0xbf3ca003,0xbf2d1469,0xbf531849,0xbf10d3cd,0xbf655e0b,0xbee363fa,0xbf731447,0xbea09ae5,0xbf7bf531,0xbe354098,0xbf7fd397,0xbd16c32c,0xbf7e9bc9,0x3dd53db9,
0xbf3504f3,0xbf3504f3,0xbf4d9f02,0xbf187fc0,0xbf61c598,0xbef15aea,0xbf710908,0xbeac7cd4,0xbf7b14be,0xbe47c5c2,0xbf7fb10f,0xbd48fb30,0xbf7ec46d,0x3dc8bd36,0xbf7853f8,0x3e78cfcc,
0xbf6c835e,0xbec3ef15,0xbf79c79d,0xbe605c13,0xbf7fb10f,0xbd48fb30,0xbf7e1324,0x3dfab273,0xbf74fa0b,0x3e94a031,0xbf64aa59,0x3ee63375,0xbf4d9f02,0x3f187fc0,0xbf3085bb,0x3f396842,
0xbf45e403,0xbf226799,0xbf5c61c7,0xbf0242b1,0xbf6db293,0xbebe1d4a,0xbf796e4e,0xbe667c66,0xbf7f4e6d,0xbd96a905,0xbf7f2f9d,0x3da3308c,0xbf791298,0x3e6c9a7f,0xbf6d1c1d,0x3ec1071e,
0xbf74fa0b,0xbe94a031,0xbf7e4323,0xbdee3876,0xbf7f84ab,0x3d7b2b74,0xbf78b47b,0x3e72b651,0xbf6a09a7,0x3ecf7bca,0xbf53fac3,0x3f0f8784,0xbf373a23,0x3f32c8c9,0xbf14b039,0x3f5064af,
0xbf54db31,0xbf0e39da,0xbf68bf3c,0xbed53641,0xbf76ba07,0xbe888e93,0xbf7e70b0,0xbde1bc2e,0xbf7fb10f,0x3d48fb30,0xbf7a7302,0x3e541501,0xbf6ed89e,0x3eb8442a,0xbf5d2d53,0x3f00e7e4,
0xbf7b14be,0xbe47c5c2,0xbf7ffb11,0xbc490e90,0xbf7c3b28,0x3e2f10a2,0xbf6ff573,0x3eb263ef,0xbf5b941a,0x3f039c3d,0xbf3fc767,0x3f299415,0xbf1d7fd1,0x3f49d112,0xbeebcbbb,0x3f633c5a,
0xbf61c598,0xbef15aea,0xbf7294f8,0xbea395c5,0xbf7cbfc9,0xbe22abb6,0xbf7ffec4,0x3bc90f88,0xbf7c3b28,0x3e2f10a2,0xbf718f57,0x3ea986c4,0xbf604621,0x3ef6e0cb,0xbf48d8b3,0x3f1ebc12,
0xbf7ec46d,0xbdc8bd36,0xbf7eea9d,0x3dbc3ac3,0xbf75dec6,0x3e8e9a22,0xbf63f473,0x3ee900b7,0xbf49d112,0x3f1d7fd1,0xbf286605,0x3f40d0da,0xbf00e7e4,0x3f5d2d53,0xbea986c4,0x3f718f57,
0x3f800000,0x0,0x3f800000,0x0,0x3f800000,0x0,0x3f800000,0x0,0x3f800000,0x0,0x3f800000,0x0,0x3f800000,0x0,0x3f800000,0x0,
0x3f54db31,0xbf0e39da,0x3f514d3d,0xbf13682a,0x3f4d9f02,0xbf187fc0,0x3f49d112,0xbf1d7fd1,0x3f45e403,0xbf226799,0x3f41d870,0xbf273656,0x3f3daef9,0xbf2beb4a,0x3f396842,0xbf3085bb,
0x3f7d3aac,0xbe164083,0x3f7cfe73,0xbe1c76de,0x3f7cbfc9,0xbe22abb6,0x3f7c7eb0,0xbe28defc,0x3f7c3b28,0xbe2f10a2,0x3f7bf531,0xbe354098,0x3f7baccd,0xbe3b6ecf,0x3f7b61fc,0xbe419b37,
0x3f3daef9,0xbf2beb4a,0x3f385216,0xbf31a81d,0x3f32c8c9,0xbf373a23,0x3f2d1469,0xbf3ca003,0x3f273656,0xbf41d870,0x3f212ff9,0xbf46e22a,0x3f1b02c6,0xbf4bbbf8,0x3f14b039,0xbf5064af,
0x3f74fa0b,0xbe94a031,0x3f740bdd,0xbe9aa086,0x3f731447,0xbea09ae5,0x3f721352,0xbea68f12,0x3f710908,0xbeac7cd4,0x3f6ff573,0xbeb263ef,0x3f6ed89e,0xbeb8442a,0x3f6db293,0xbebe1d4a,
0x3f226799,0xbf45e403,0x3f1b02c6,0xbf4bbbf8,0x3f13682a,0xbf514d3d,0x3f0b9a6b,0xbf5695e5,0x3f039c3d,0xbf5b941a,0x3ef6e0cb,0xbf604621,0x3ee63375,0xbf64aa59,0x3ed53641,0xbf68bf3c,
0x3f676bd8,0xbedae880,0x3f655e0b,0xbee363fa,0x3f633c5a,0xbeebcbbb,0x3f6106f2,0xbef41f07,0x3f5ebe05,0xbefc5d27,0x3f5c61c7,0xbf0242b1,0x3f59f26a,0xbf064b82,0x3f577026,0xbf0a48ad,
0x3f039c3d,0xbf5b941a,0x3ef41f07,0xbf6106f2,0x3ee0924f,0xbf660f88,0x3ecc9b8b,0xbf6aab7b,0x3eb8442a,0xbf6ed89e,0x3ea395c5,0xbf7294f8,0x3e8e9a22,0xbf75dec6,0x3e72b651,0xbf78b47b,
0x3ec3ef15,0xbf6c835e,0x3eac7cd4,0xbf710908,0x3e94a031,0xbf74fa0b,0x3e78cfcc,0xbf7853f8,0x3e47c5c2,0xbf7b14be,0x3e164083,0xbf7d3aac,0x3dc8bd36,0xbf7ec46d,0x3d48fb30,0xbf7fb10f,
0xbe47c5c2,0xbf7b14be,0xbe888e93,0xbf76ba07,0xbeac7cd4,0xbf710908,0xbecf7bca,0xbf6a09a7,0xbef15aea,0xbf61c598,0xbf08f59b,0xbf584853,0xbf187fc0,0xbf4d9f02,0xbf273656,0xbf41d870,
0x3e78cfcc,0xbf7853f8,0x3e419b37,0xbf7b61fc,0x3e09cf86,0xbf7dabcc,0x3da3308c,0xbf7f2f9d,0x3cc90ab0,0xbf7fec43,0xbcfb49ba,0xbf7fe129,0xbdafb680,0xbf7f0e58,0xbe1008b7,0xbf7d7474,
0xbeac7cd4,0xbf710908,0xbed25a09,0xbf696591,0xbef6e0cb,0xbf604621,0xbf0cead0,0xbf55b993,0xbf1d7fd1,0xbf49d112,0xbf2d1469,0xbf3ca003,0xbf3b8f3b,0xbf2e3bde,0xbf48d8b3,0xbf1ebc12,
0x3dc8bd36,0xbf7ec46d,0x3d16c32c,0xbf7fd397,0xbcc90ab0,0xbf7fec43,0xbdafb680,0xbf7f0e58,0xbe164083,0xbf7d3aac,0xbe541501,0xbf7a7302,0xbe888e93,0xbf76ba07,0xbea68f12,0xbf721352,
0xbef15aea,0xbf61c598,0xbf0b9a6b,0xbf5695e5,0xbf1d7fd1,0xbf49d112,0xbf2e3bde,0xbf3b8f3b,0xbf3daef9,0xbf2beb4a,0xbf4bbbf8,0xbf1b02c6,0xbf584853,0xbf08f59b,0xbf633c5a,0xbeebcbbb,
0xbd48fb30,0xbf7fb10f,0xbdee3876,0xbf7e4323,0xbe3b6ecf,0xbf7baccd,0xbe7ee6e1,0xbf77f110,0xbea09ae5,0xbf731447,0xbec1071e,0xbf6d1c1d,0xbee0924f,0xbf660f88,0xbeff17b2,0xbf5df6be,
0xbf187fc0,0xbf4d9f02,0xbf2ac082,0xbf3ebc1b,0xbf3b8f3b,0xbf2e3bde,0xbf4ac77f,0xbf1c420c,0xbf584853,0xbf08f59b,0xbf63f473,0xbee900b7,0xbf6db293,0xbebe1d4a,0xbf756d97,0xbe919ddd,
0xbf3504f3,0xbf3504f3,0xbf45e403,0xbf226799,0xbf54db31,0xbf0e39da,0xbf61c598,0xbef15aea,0xbf6c835e,0xbec3ef15,0xbf74fa0b,0xbe94a031,0xbf7b14be,0xbe47c5c2,0xbf7ec46d,0xbdc8bd36,
0xbf7b14be,0xbe47c5c2,0xbf7f4e6d,0xbd96a905,0xbf7fb10f,0x3d48fb30,0xbf7c3b28,0x3e2f10a2,0xbf74fa0b,0x3e94a031,0xbf6a09a7,0x3ecf7bca,0xbf5b941a,0x3f039c3d,0xbf49d112,0x3f1d7fd1,
0xbf4d9f02,0xbf187fc0,0xbf5c61c7,0xbf0242b1,0xbf68bf3c,0xbed53641,0xbf7294f8,0xbea395c5,0xbf79c79d,0xbe605c13,0xbf7e4323,0xbdee3876,0xbf7ffb11,0xbc490e90,0xbf7eea9d,0x3dbc3ac3,
0xbf7fb10f,0xbd48fb30,0xbf7f2f9d,0x3da3308c,0xbf7a7302,0x3e541501,0xbf718f57,0x3ea986c4,0xbf64aa59,0x3ee63375,0xbf53fac3,0x3f0f8784,0xbf3fc767,0x3f299415,0xbf286605,0x3f40d0da,
0xbf61c598,0xbef15aea,0xbf6db293,0xbebe1d4a,0xbf76ba07,0xbe888e93,0xbf7cbfc9,0xbe22abb6,0xbf7fb10f,0xbd48fb30,0xbf7f84ab,0x3d7b2b74,0xbf7c3b28,0x3e2f10a2,0xbf75dec6,0x3e8e9a22,
0xbf7ec46d,0x3dc8bd36,0xbf791298,0x3e6c9a7f,0xbf6ed89e,0x3eb8442a,0xbf604621,0x3ef6e0cb,0xbf4d9f02,0x3f187fc0,0xbf373a23,0x3f32c8c9,0xbf1d7fd1,0x3f49d112,0xbf00e7e4,0x3f5d2d53,
0xbf710908,0xbeac7cd4,0xbf796e4e,0xbe667c66,0xbf7e70b0,0xbde1bc2e,0xbf7ffec4,0x3bc90f88,0xbf7e1324,0x3dfab273,0xbf78b47b,0x3e72b651,0xbf6ff573,0x3eb263ef,0xbf63f473,0x3ee900b7,
0xbf7853f8,0x3e78cfcc,0xbf6d1c1d,0x3ec1071e,0xbf5d2d53,0x3f00e7e4,0xbf48d8b3,0x3f1ebc12,0xbf3085bb,0x3f396842,0xbf14b039,0x3f5064af,0xbeebcbbb,0x3f633c5a,0xbea986c4,0x3f718f57,
0xbf6c835e,0x3ec3ef15,0xbf5b941a,0x3f039c3d,0xbf45e403,0x3f226799,0xbf2beb4a,0x3f3daef9,0xbf0e39da,0x3f54db31,0xbedae880,0x3f676bd8,0xbe94a031,0x3f74fa0b,0xbe164083,0x3f7d3aac,
0xbf0e39da,0x3f54db31,0xbecf7bca,0x3f6a09a7,0xbe78cfcc,0x3f7853f8,0xbd96a905,0x3f7f4e6d,0x3dc8bd36,0x3f7ec46d,0x3e888e93,0x3f76ba07,0x3edae880,0x3f676bd8,0x3f13682a,0x3f514d3d,
0xbf5b941a,0x3f039c3d,0xbf44e3f5,0x3f239da9,0xbf299415,0x3f3fc767,0xbf0a48ad,0x3f577026,0xbecf7bca,0x3f6a09a7,0xbe8586ce,0x3f772417,0xbde1bc2e,0x3f7e70b0,0x3d2fe007,0x3f7fc38f,
0xbedae880,0x3f676bd8,0xbe8586ce,0x3f772417,0xbdafb680,0x3f7f0e58,0x3dbc3ac3,0x3f7eea9d,0x3e888e93,0x3f76ba07,0x3eddbe79,0x3f66becc,0x3f15f6d9,0x3f4f7a1f,0x3f385216,0x3f31a81d,
0xbf45e403,0x3f226799,0xbf299415,0x3f3fc767,0xbf08f59b,0x3f584853,0xbec9b953,0x3f6b4b0c,0xbe78cfcc,0x3f7853f8,0xbdafb680,0x3f7f0e58,0x3d96a905,0x3f7f4e6d,0x3e6c9a7f,0x3f791298,
0xbe94a031,0x3f74fa0b,0xbde1bc2e,0x3f7e70b0,0x3d96a905,0x3f7f4e6d,0x3e827dc0,0x3f778bc5,0x3edae880,0x3f676bd8,0x3f15f6d9,0x3f4f7a1f,0x3f396842,0x3f3085bb,0x3f5695e5,0x3f0b9a6b,
0xbf2beb4a,0x3f3daef9,0xbf0a48ad,0x3f577026,0xbec9b953,0x3f6b4b0c,0xbe72b651,0x3f78b47b,0xbd96a905,0x3f7f4e6d,0x3dbc3ac3,0x3f7eea9d,0x3e827dc0,0x3f778bc5,0x3ed25a09,0x3f696591,
0xbe164083,0x3f7d3aac,0x3d2fe007,0x3f7fc38f,0x3e6c9a7f,0x3f791298,0x3ed25a09,0x3f696591,0x3f13682a,0x3f514d3d,0x3f385216,0x3f31a81d,0x3f5695e5,0x3f0b9a6b,0x3f6d1c1d,0x3ec1071e,
0x3e00,0x3e00,0x3e00,0x3e00,0x3e00,0x3e00,0x3e00,0x3e00,0x3e00,0x3e00,0x3e00,0x3e00,0x3e00,0x3e00,0x3e00,0x3e00,
0xbd443ded,0xbcc83dfb,0xbc493dff,0xbd153df5,0xbdb53db5,0xbdd53d8e,0xbdc63da2,0xbde23d71,0xbe000000,0xbdfbbcc8,0xbdffbc49,0xbdf5bd15,0xbdb5bdb5,0xbd8ebdd5,0xbda2bdc6,0xbd71bde2,
0xbdb53db5,0xbd443ded,0xbcc83dfb,0xbd8e3dd5,0xbe000000,0xbdedbd44,0xbdfbbcc8,0xbdd5bd8e,0xbe00,0x3d44bded,0x3cc8bdfb,0x3d8ebdd5,0x3e000000,0x3ded3d44,0x3dfb3cc8,0x3dd53d8e,
0xbded3d44,0xbd8e3dd5,0xbd153df5,0xbdc63da2,0xbdb5bdb5,0xbcc8bdfb,0xbd71bde2,0x3c49bdff,0x3e000000,0x3dd53d8e,0x3df53d15,0x3da23dc6,0xbdb53db5,0xbdfb3cc8,0xbde23d71,0xbdffbc49,
0xbe000000,0xbdb53db5,0xbd443ded,0xbded3d44,0xbe00,0x3db5bdb5,0x3d44bded,0x3dedbd44,0x3e00,0xbdb53db5,0xbd443ded,0xbded3d44,0xbe00,0x3db5bdb5,0x3d44bded,0x3dedbd44,
0xbdedbd44,0xbdd53d8e,0xbd713de2,0xbdff3c49,0x3db5bdb5,0x3dfb3cc8,0x3df5bd15,0x3dc63da2,0xbe000000,0xbd8ebdd5,0xbde2bd71,0xbc49bdff,0x3db53db5,0xbcc83dfb,0x3d153df5,0xbda23dc6,
0xbdb5bdb5,0xbded3d44,0xbd8e3dd5,0xbdfbbcc8,0x3e000000,0x3d443ded,0x3dd53d8e,0xbcc83dfb,0xbe00,0x3dedbd44,0x3d8ebdd5,0x3dfb3cc8,0xbe000000,0xbd44bded,0xbdd5bd8e,0x3cc8bdfb,
0xbd44bded,0xbdfb3cc8,0xbda23dc6,0xbde2bd71,0x3db53db5,0xbd8e3dd5,0x3c493dff,0xbdf53d15,0x3e000000,0x3cc83dfb,0x3dc63da2,0xbd713de2,0x3db5bdb5,0x3dd53d8e,0x3dffbc49,0x3d153df5,
0xbe00,0xbe000000,0xbdb53db5,0xbdb5bdb5,0x3e00,0xbe000000,0xbdb53db5,0xbdb5bdb5,0x3e00,0xbe000000,0xbdb53db5,0xbdb5bdb5,0x3e00,0xbe000000,0xbdb53db5,0xbdb5bdb5,
0x3d44bded,0xbdfbbcc8,0xbdc63da2,0xbd71bde2,0xbdb53db5,0xbd8ebdd5,0xbdffbc49,0x3d15bdf5,0xbe000000,0x3cc8bdfb,0xbda2bdc6,0x3de2bd71,0xbdb5bdb5,0x3dd5bd8e,0x3c49bdff,0x3df53d15,
0x3db5bdb5,0xbdedbd44,0xbdd53d8e,0xbcc8bdfb,0xbe000000,0x3d44bded,0xbd8ebdd5,0x3dfbbcc8,0xbe00,0x3ded3d44,0x3dd5bd8e,0x3cc83dfb,0x3e000000,0xbd443ded,0x3d8e3dd5,0xbdfb3cc8,
0x3dedbd44,0xbdd5bd8e,0xbde23d71,0x3c49bdff,0xbdb5bdb5,0x3dfbbcc8,0x3d15bdf5,0x3da23dc6,0x3e000000,0xbd8e3dd5,0x3d713de2,0xbdffbc49,0xbdb53db5,0xbcc8bdfb,0xbdf5bd15,0x3dc6bda2,
0x3e000000,0xbdb5bdb5,0xbded3d44,0x3d44bded,0xbe00,0x3db53db5,0x3dedbd44,0xbd443ded,0x3e00,0xbdb5bdb5,0xbded3d44,0x3d44bded,0xbe00,0x3db53db5,0x3dedbd44,0xbd443ded,
0x3ded3d44,0xbd8ebdd5,0xbdf53d15,0x3da2bdc6,0x3db5bdb5,0xbcc83dfb,0x3de23d71,0xbdff3c49,0xbe000000,0x3dd5bd8e,0xbd15bdf5,0x3dc63da2,0x3db53db5,0xbdfbbcc8,0xbd713de2,0xbc49bdff,
0x3db53db5,0xbd44bded,0xbdfb3cc8,0x3dd5bd8e,0x3e000000,0xbded3d44,0x3cc83dfb,0xbd8ebdd5,0xbe00,0x3d443ded,0x3dfbbcc8,0xbdd53d8e,0xbe000000,0x3dedbd44,0xbcc8bdfb,0x3d8e3dd5,
0x3d443ded,0xbcc8bdfb,0xbdff3c49,0x3df5bd15,0x3db53db5,0xbdd5bd8e,0xbda23dc6,0x3d71bde2,0x3e000000,0xbdfb3cc8,0x3c493dff,0xbd15bdf5,0x3db5bdb5,0xbd8e3dd5,0x3dc63da2,0xbde2bd71,
0x3e00,0xbe00,0xbe000000,0x3e000000,0x3e00,0xbe00,0xbe000000,0x3e000000,0x3e00,0xbe00,0xbe000000,0x3e000000,0x3e00,0xbe00,0xbe000000,0x3e000000,
0xbd443ded,0x3cc8bdfb,0xbdffbc49,0x3df53d15,0xbdb53db5,0x3dd5bd8e,0xbda2bdc6,0x3d713de2,0xbe000000,0x3dfb3cc8,0x3c49bdff,0xbd153df5,0xbdb5bdb5,0x3d8e3dd5,0x3dc6bda2,0xbde23d71,
0xbdb53db5,0x3d44bded,0xbdfbbcc8,0x3dd53d8e,0xbe000000,0x3ded3d44,0x3cc8bdfb,0xbd8e3dd5,0xbe00,0xbd443ded,0x3dfb3cc8,0xbdd5bd8e,0x3e000000,0xbdedbd44,0xbcc83dfb,0x3d8ebdd5,
0xbded3d44,0x3d8ebdd5,0xbdf5bd15,0x3da23dc6,0xbdb5bdb5,0x3cc83dfb,0x3de2bd71,0xbdffbc49,0x3e000000,0xbdd5bd8e,0xbd153df5,0x3dc6bda2,0xbdb53db5,0x3dfbbcc8,0xbd71bde2,0xbc493dff,
0xbe000000,0x3db5bdb5,0xbdedbd44,0x3d443ded,0xbe00,0xbdb53db5,0x3ded3d44,0xbd44bded,0x3e00,0x3db5bdb5,0xbdedbd44,0x3d443ded,0xbe00,0xbdb53db5,0x3ded3d44,0xbd44bded,
0xbdedbd44,0x3dd5bd8e,0xbde2bd71,0x3c493dff,0x3db5bdb5,0xbdfbbcc8,0x3d153df5,0x3da2bdc6,0xbe000000,0x3d8e3dd5,0x3d71bde2,0xbdff3c49,0x3db53db5,0x3cc8bdfb,0xbdf53d15,0x3dc63da2,
0xbdb5bdb5,0x3dedbd44,0xbdd5bd8e,0xbcc83dfb,0x3e000000,0xbd44bded,0xbd8e3dd5,0x3dfb3cc8,0xbe00,0xbded3d44,0x3dd53d8e,0x3cc8bdfb,0xbe000000,0x3d443ded,0x3d8ebdd5,0xbdfbbcc8,
0xbd44bded,0x3dfbbcc8,0xbdc6bda2,0xbd713de2,0x3db53db5,0x3d8ebdd5,0xbdff3c49,0x3d153df5,0x3e000000,0xbcc8bdfb,0xbda23dc6,0x3de23d71,0x3db5bdb5,0xbdd5bd8e,0x3c493dff,0x3df5bd15,
0xbe00,0x3e000000,0xbdb5bdb5,0xbdb53db5,0x3e00,0x3e000000,0xbdb5bdb5,0xbdb53db5,0x3e00,0x3e000000,0xbdb5bdb5,0xbdb53db5,0x3e00,0x3e000000,0xbdb5bdb5,0xbdb53db5,
0x3d44bded,0x3dfb3cc8,0xbda2bdc6,0xbde23d71,0xbdb53db5,0x3d8e3dd5,0x3c49bdff,0xbdf5bd15,0xbe000000,0xbcc83dfb,0x3dc6bda2,0xbd71bde2,0xbdb5bdb5,0xbdd53d8e,0x3dff3c49,0x3d15bdf5,
0x3db5bdb5,0x3ded3d44,0xbd8ebdd5,0xbdfb3cc8,0xbe000000,0xbd443ded,0x3dd5bd8e,0xbcc8bdfb,0xbe00,0xbdedbd44,0x3d8e3dd5,0x3dfbbcc8,0x3e000000,0x3d44bded,0xbdd53d8e,0x3cc83dfb,
0x3dedbd44,0x3dd53d8e,0xbd71bde2,0xbdffbc49,0xbdb5bdb5,0xbdfb3cc8,0x3df53d15,0x3dc6bda2,0x3e000000,0x3d8ebdd5,0xbde23d71,0xbc493dff,0xbdb53db5,0x3cc83dfb,0x3d15bdf5,0xbda2bdc6,
0x3e000000,0x3db53db5,0xbd44bded,0xbdedbd44,0xbe00,0xbdb5bdb5,0x3d443ded,0x3ded3d44,0x3e00,0x3db53db5,0xbd44bded,0xbdedbd44,0xbe00,0xbdb5bdb5,0x3d443ded,0x3ded3d44,
0x3ded3d44,0x3d8e3dd5,0xbd15bdf5,0xbdc6bda2,0x3db5bdb5,0x3cc8bdfb,0xbd713de2,0x3c493dff,0xbe000000,0xbdd53d8e,0x3df5bd15,0x3da2bdc6,0x3db53db5,0x3dfb3cc8,0xbde2bd71,0xbdff3c49,
0x3db53db5,0x3d443ded,0xbcc8bdfb,0xbd8ebdd5,0x3e000000,0x3dedbd44,0xbdfb3cc8,0xbdd53d8e,0xbe00,0xbd44bded,0x3cc83dfb,0x3d8e3dd5,0xbe000000,0xbded3d44,0x3dfbbcc8,0x3dd5bd8e,
0x3d443ded,0x3cc83dfb,0xbc49bdff,0xbd15bdf5,0x3db53db5,0x3dd53d8e,0xbdc6bda2,0xbde2bd71,0x3e000000,0x3dfbbcc8,0xbdff3c49,0xbdf53d15,0x3db5bdb5,0x3d8ebdd5,0xbda23dc6,0xbd713de2,
0x3d803d80,0x3e00,0x3e00,0x3e00,0x3e00,0x3e00,0x3e00,0x3e00,0x3e00,0x3e00,0x3e00,0x3e00,0x3e00,0x3e00,0x3e00,0x3e00,
0xbd803d80,0x3cc8bdfb,0x3c49bdff,0x3d15bdf5,0xbded3d44,0x3dd5bd8e,0x3dc6bda2,0x3de2bd71,0xbdedbd44,0x3dfb3cc8,0x3dff3c49,0x3df53d15,0xbd44bded,0x3d8e3dd5,0x3da23dc6,0x3d713de2,
0x3d803d80,0xbd443ded,0xbcc83dfb,0xbd8e3dd5,0xbdb5bdb5,0xbdedbd44,0xbdfbbcc8,0xbdd5bd8e,0x3db5bdb5,0x3d44bded,0x3cc8bdfb,0x3d8ebdd5,0x3db53db5,0x3ded3d44,0x3dfb3cc8,0x3dd53d8e,
0xbd803d80,0x3d8ebdd5,0x3d15bdf5,0x3dc6bda2,0x3d44bded,0x3cc83dfb,0x3d713de2,0xbc493dff,0x3d443ded,0xbdd5bd8e,0xbdf5bd15,0xbda2bdc6,0xbdedbd44,0x3dfbbcc8,0x3de2bd71,0x3dff3c49,
0x3d803d80,0xbdb53db5,0xbd443ded,0xbded3d44,0x3e000000,0x3db5bdb5,0x3d44bded,0x3dedbd44,0xbe000000,0xbdb53db5,0xbd443ded,0xbded3d44,0x3e000000,0x3db5bdb5,0x3d44bded,0x3dedbd44,
0xbd803d80,0x3dd5bd8e,0x3d71bde2,0x3dffbc49,0x3d443ded,0xbdfbbcc8,0xbdf53d15,0xbdc6bda2,0x3d44bded,0x3d8e3dd5,0x3de23d71,0x3c493dff,0xbded3d44,0x3cc8bdfb,0xbd15bdf5,0x3da2bdc6,
0x3d803d80,0xbded3d44,0xbd8e3dd5,0xbdfbbcc8,0xbdb53db5,0x3d443ded,0x3dd53d8e,0xbcc83dfb,0x3db53db5,0x3dedbd44,0x3d8ebdd5,0x3dfb3cc8,0x3db5bdb5,0xbd44bded,0xbdd5bd8e,0x3cc8bdfb,
0xbd803d80,0x3dfbbcc8,0x3da2bdc6,0x3de23d71,0xbdedbd44,0x3d8ebdd5,0xbc49bdff,0x3df5bd15,0xbded3d44,0xbcc8bdfb,0xbdc6bda2,0x3d71bde2,0xbd443ded,0xbdd5bd8e,0xbdff3c49,0xbd15bdf5,
0x3d803d80,0xbe000000,0xbdb53db5,0xbdb5bdb5,0xbe00,0xbe000000,0xbdb53db5,0xbdb5bdb5,0xbe00,0xbe000000,0xbdb53db5,0xbdb5bdb5,0xbe00,0xbe000000,0xbdb53db5,0xbdb5bdb5,
0xbd803d80,0x3dfb3cc8,0x3dc6bda2,0x3d713de2,0x3dedbd44,0x3d8e3dd5,0x3dff3c49,0xbd153df5,0x3ded3d44,0xbcc83dfb,0x3da23dc6,0xbde23d71,0x3d443ded,0xbdd53d8e,0xbc493dff,0xbdf5bd15,
0x3d803d80,0xbdedbd44,0xbdd53d8e,0xbcc8bdfb,0x3db53db5,0x3d44bded,0xbd8ebdd5,0x3dfbbcc8,0xbdb53db5,0x3ded3d44,0x3dd5bd8e,0x3cc83dfb,0xbdb5bdb5,0xbd443ded,0x3d8e3dd5,0xbdfb3cc8,
0xbd803d80,0x3dd53d8e,0x3de2bd71,0xbc493dff,0xbd443ded,0xbdfb3cc8,0xbd153df5,0xbda2bdc6,0xbd44bded,0x3d8ebdd5,0xbd71bde2,0x3dff3c49,0x3ded3d44,0x3cc83dfb,0x3df53d15,0xbdc63da2,
0x3d803d80,0xbdb5bdb5,0xbded3d44,0x3d44bded,0xbe000000,0x3db53db5,0x3dedbd44,0xbd443ded,0x3e000000,0xbdb5bdb5,0xbded3d44,0x3d44bded,0xbe000000,0x3db53db5,0x3dedbd44,0xbd443ded,
0xbd803d80,0x3d8e3dd5,0x3df5bd15,0xbda23dc6,0xbd44bded,0x3cc8bdfb,0xbde2bd71,0x3dffbc49,0xbd443ded,0xbdd53d8e,0x3d153df5,0xbdc6bda2,0x3dedbd44,0x3dfb3cc8,0x3d71bde2,0x3c493dff,
0x3d803d80,0xbd44bded,0xbdfb3cc8,0x3dd5bd8e,0x3db5bdb5,0xbded3d44,0x3cc83dfb,0xbd8ebdd5,0xbdb5bdb5,0x3d443ded,0x3dfbbcc8,0xbdd53d8e,0xbdb53db5,0x3dedbd44,0xbcc8bdfb,0x3d8e3dd5,
0xbd803d80,0x3cc83dfb,0x3dffbc49,0xbdf53d15,0x3ded3d44,0x3dd53d8e,0x3da2bdc6,0xbd713de2,0x3dedbd44,0x3dfbbcc8,0xbc49bdff,0x3d153df5,0x3d44bded,0x3d8ebdd5,0xbdc6bda2,0x3de23d71,
0x3d803d80,0xbe00,0xbe000000,0x3e000000,0x3e00,0xbe00,0xbe000000,0x3e000000,0x3e00,0xbe00,0xbe000000,0x3e000000,0x3e00,0xbe00,0xbe000000,0x3e000000,
0xbd803d80,0xbcc83dfb,0x3dff3c49,0xbdf5bd15,0xbded3d44,0xbdd53d8e,0x3da23dc6,0xbd71bde2,0xbdedbd44,0xbdfbbcc8,0xbc493dff,0x3d15bdf5,0xbd44bded,0xbd8ebdd5,0xbdc63da2,0x3de2bd71,
0x3d803d80,0x3d44bded,0xbdfbbcc8,0x3dd53d8e,0xbdb5bdb5,0x3ded3d44,0x3cc8bdfb,0xbd8e3dd5,0x3db5bdb5,0xbd443ded,0x3dfb3cc8,0xbdd5bd8e,0x3db53db5,0xbdedbd44,0xbcc83dfb,0x3d8ebdd5,
0xbd803d80,0xbd8e3dd5,0x3df53d15,0xbda2bdc6,0x3d44bded,0xbcc8bdfb,0xbde23d71,0x3dff3c49,0x3d443ded,0x3dd53d8e,0x3d15bdf5,0xbdc63da2,0xbdedbd44,0xbdfb3cc8,0x3d713de2,0x3c49bdff,
0x3d803d80,0x3db5bdb5,0xbdedbd44,0x3d443ded,0x3e000000,0xbdb53db5,0x3ded3d44,0xbd44bded,0xbe000000,0x3db5bdb5,0xbdedbd44,0x3d443ded,0x3e000000,0xbdb53db5,0x3ded3d44,0xbd44bded,
0xbd803d80,0xbdd53d8e,0x3de23d71,0xbc49bdff,0x3d443ded,0x3dfb3cc8,0xbd15bdf5,0xbda23dc6,0x3d44bded,0xbd8ebdd5,0xbd713de2,0x3dffbc49,0xbded3d44,0xbcc83dfb,0x3df5bd15,0xbdc6bda2,
0x3d803d80,0x3dedbd44,0xbdd5bd8e,0xbcc83dfb,0xbdb53db5,0xbd44bded,0xbd8e3dd5,0x3dfb3cc8,0x3db53db5,0xbded3d44,0x3dd53d8e,0x3cc8bdfb,0x3db5bdb5,0x3d443ded,0x3d8ebdd5,0xbdfbbcc8,
0xbd803d80,0xbdfb3cc8,0x3dc63da2,0x3d71bde2,0xbdedbd44,0xbd8e3dd5,0x3dffbc49,0xbd15bdf5,0xbded3d44,0x3cc83dfb,0x3da2bdc6,0xbde2bd71,0xbd443ded,0x3dd53d8e,0xbc49bdff,0xbdf53d15,
0x3d803d80,0x3e000000,0xbdb5bdb5,0xbdb53db5,0xbe00,0x3e000000,0xbdb5bdb5,0xbdb53db5,0xbe00,0x3e000000,0xbdb5bdb5,0xbdb53db5,0xbe00,0x3e000000,0xbdb5bdb5,0xbdb53db5,
0xbd803d80,0xbdfbbcc8,0x3da23dc6,0x3de2bd71,0x3dedbd44,0xbd8ebdd5,0xbc493dff,0x3df53d15,0x3ded3d44,0x3cc8bdfb,0xbdc63da2,0x3d713de2,0x3d443ded,0x3dd5bd8e,0xbdffbc49,0xbd153df5,
0x3d803d80,0x3ded3d44,0xbd8ebdd5,0xbdfb3cc8,0x3db53db5,0xbd443ded,0x3dd5bd8e,0xbcc8bdfb,0xbdb53db5,0xbdedbd44,0x3d8e3dd5,0x3dfbbcc8,0xbdb5bdb5,0x3d44bded,0xbdd53d8e,0x3cc83dfb,
0xbd803d80,0xbdd5bd8e,0x3d713de2,0x3dff3c49,0xbd443ded,0x3dfbbcc8,0xbdf5bd15,0xbdc63da2,0xbd44bded,0xbd8e3dd5,0x3de2bd71,0x3c49bdff,0x3ded3d44,0xbcc8bdfb,0xbd153df5,0x3da23dc6,
0x3d803d80,0x3db53db5,0xbd44bded,0xbdedbd44,0xbe000000,0xbdb5bdb5,0x3d443ded,0x3ded3d44,0x3e000000,0x3db53db5,0xbd44bded,0xbdedbd44,0xbe000000,0xbdb5bdb5,0x3d443ded,0x3ded3d44,
0xbd803d80,0xbd8ebdd5,0x3d153df5,0x3dc63da2,0xbd44bded,0xbcc83dfb,0x3d71bde2,0xbc49bdff,0xbd443ded,0x3dd5bd8e,0xbdf53d15,0xbda23dc6,0x3dedbd44,0xbdfbbcc8,0x3de23d71,0x3dffbc49,
0x3d803d80,0x3d443ded,0xbcc8bdfb,0xbd8ebdd5,0x3db5bdb5,0x3dedbd44,0xbdfb3cc8,0xbdd53d8e,0xbdb5bdb5,0xbd44bded,0x3cc83dfb,0x3d8e3dd5,0xbdb53db5,0xbded3d44,0x3dfbbcc8,0x3dd5bd8e,
0xbd803d80,0xbcc8bdfb,0x3c493dff,0x3d153df5,0x3ded3d44,0xbdd5bd8e,0x3dc63da2,0x3de23d71,0x3dedbd44,0xbdfb3cc8,0x3dffbc49,0x3df5bd15,0x3d44bded,0xbd8e3dd5,0x3da2bdc6,0x3d71bde2,
0xbc493dff,0xbbc93e00,0xbb493e00,0xbc173dff,0xbcc83dfb,0xbcf93df8,0xbce03dfa,0xbd093df7,0xbd443ded,0xbd5b3de7,0xbd4f3dea,0xbd663de5,0xbd8e3dd5,0xbd983dce,0xbd933dd1,0xbd9d3dca,
0xbd713de2,0xbcf93df8,0xbc7b3dfe,0xbd383def,0xbdd53d8e,0xbdf13d2c,0xbde53d66,0xbdfa3ce0,0xbdedbd44,0xbdcebd98,0xbddfbd7c,0xbdb9bdb1,0xbcc8bdfb,0x3bc9be00,0xbc17bdff,0x3cafbdfc,
0xbdc63da2,0xbd5b3de7,0xbce03dfa,0xbd9d3dca,0xbdfbbcc8,0xbdcebd98,0xbdeabd4f,0xbda7bdc2,0x3d44bded,0x3dbebdac,0x3d93bdd1,0x3ddfbd7c,0x3dd53d8e,0x3d843ddc,0x3db13db9,0x3d213df3,
0xbdf53d15,0xbd983dce,0xbd213df3,0xbdd13d93,0xbd8ebdd5,0x3bc9be00,0xbd09bdf7,0x3d38bdef,0x3ded3d44,0x3d843ddc,0x3dc23da7,0x3ce03dfa,0xbdfb3cc8,0xbde7bd5b,0xbdfebc7b,0xbdb9bdb1,
0xbdffbc49,0xbdbe3dac,0xbd4f3dea,0xbdf33d21,0x3cc8bdfb,0x3ddcbd84,0x3d93bdd1,0x3dfebc7b,0xbd443ded,0xbdf13d2c,0xbdb93db1,0xbdffbc17,0x3d8ebdd5,0x3dfdbc96,0x3dd8bd89,0x3df73d09,
0xbde2bd71,0xbddc3d84,0xbd7c3ddf,0xbe003b49,0x3dd5bd8e,0x3de73d5b,0x3dffbc17,0x3d933dd1,0xbdedbd44,0xbc96bdfd,0xbd9dbdca,0x3d38bdef,0x3cc83dfb,0xbdbe3dac,0xbd213df3,0xbdfa3ce0,
0xbda2bdc6,0xbdf13d2c,0xbd933dd1,0xbdf7bd09,0x3dfb3cc8,0x3c963dfd,0x3db13db9,0xbd663de5,0x3d44bded,0x3e003bc9,0x3dd8bd89,0x3dca3d9d,0xbdd5bd8e,0x3cf9bdf8,0xbd38bdef,0x3dc2bda7,
0xbd15bdf5,0xbdfd3c96,0xbda73dc2,0xbdd8bd89,0x3d8e3dd5,0xbdbe3dac,0xbc7b3dfe,0xbe003b49,0x3ded3d44,0xbcf93df8,0x3d663de5,0xbdd13d93,0x3dfbbcc8,0x3d2c3df1,0x3ddf3d7c,0xbd383def,
0x3c49bdff,0xbe00bbc9,0xbdb93db1,0xbda7bdc2,0xbcc83dfb,0xbdf8bcf9,0xbdd83d89,0xbd7cbddf,0xbd443ded,0xbde7bd5b,0xbdef3d38,0xbd21bdf3,0xbd8e3dd5,0xbdcebd98,0xbdfc3caf,0xbc7bbdfe,
0x3d71bde2,0xbdf8bcf9,0xbdca3d9d,0xbd4fbdea,0xbdd53d8e,0xbd2cbdf1,0xbdf3bd21,0x3d89bdd8,0xbdedbd44,0x3d98bdce,0xbd09bdf7,0x3e00bb49,0xbcc8bdfb,0x3e003bc9,0x3da7bdc2,0x3d933dd1,
0x3dc6bda2,0xbde7bd5b,0xbdd83d89,0xbc7bbdfe,0xbdfbbcc8,0x3d98bdce,0xbd38bdef,0x3dff3c17,0x3d44bded,0x3dac3dbe,0x3dfcbcaf,0xbd093df7,0x3dd53d8e,0xbddc3d84,0xbb493e00,0xbde5bd66,
0x3df5bd15,0xbdcebd98,0xbde53d66,0x3cafbdfc,0xbd8ebdd5,0x3e003bc9,0x3d7cbddf,0x3d4f3dea,0x3ded3d44,0xbddc3d84,0x3c173dff,0xbdd8bd89,0xbdfb3cc8,0x3d5bbde7,0xbd9dbdca,0x3e00bb49,
0x3dff3c49,0xbdacbdbe,0xbdef3d38,0x3d66bde5,0x3cc8bdfb,0x3d843ddc,0x3dfcbcaf,0xbd9d3dca,0xbd443ded,0xbd2cbdf1,0xbe00bb49,0x3dc2bda7,0x3d8ebdd5,0x3c963dfd,0x3dfa3ce0,0xbddf3d7c,
0x3de23d71,0xbd84bddc,0xbdf73d09,0x3db1bdb9,0x3dd5bd8e,0xbd5b3de7,0x3dc23da7,0xbdfcbcaf,0xbdedbd44,0x3dfdbc96,0x3c7bbdfe,0x3d4f3dea,0x3cc83dfb,0xbdacbdbe,0xbde53d66,0x3d89bdd8,
0x3da23dc6,0xbd2cbdf1,0xbdfc3caf,0x3ddfbd7c,0x3dfb3cc8,0xbdfd3c96,0xbb493e00,0xbd21bdf3,0x3d44bded,0xbbc93e00,0x3dfa3ce0,0xbdfe3c7b,0xbdd5bd8e,0x3df83cf9,0x3d4fbdea,0xbc173dff,
0x3d153df5,0xbc96bdfd,0xbdff3c17,0x3dfabce0,0x3d8e3dd5,0xbdacbdbe,0xbdca3d9d,0x3db1bdb9,0x3ded3d44,0xbdf8bcf9,0xbd213df3,0x3cafbdfc,0x3dfbbcc8,0xbdf13d2c,0x3d093df7,0xbd4fbdea,
0xbc493dff,0x3bc9be00,0xbe00bb49,0x3dff3c17,0xbcc83dfb,0x3cf9bdf8,0xbdfabce0,0x3df73d09,0xbd443ded,0x3d5bbde7,0xbdeabd4f,0x3de53d66,0xbd8e3dd5,0x3d98bdce,0xbdd1bd93,0x3dca3d9d,
0xbd713de2,0x3cf9bdf8,0xbdfebc7b,0x3def3d38,0xbdd53d8e,0x3df1bd2c,0xbd66bde5,0x3ce03dfa,0xbdedbd44,0x3dce3d98,0x3d7cbddf,0xbdb13db9,0xbcc8bdfb,0xbbc93e00,0x3dffbc17,0xbdfcbcaf,
0xbdc63da2,0x3d5bbde7,0xbdfabce0,0x3dca3d9d,0xbdfbbcc8,0x3dce3d98,0x3d4fbdea,0xbdc23da7,0x3d44bded,0xbdbe3dac,0x3dd13d93,0xbd7cbddf,0x3dd53d8e,0xbd84bddc,0xbdb93db1,0x3df3bd21,
0xbdf53d15,0x3d98bdce,0xbdf3bd21,0x3d933dd1,0xbd8ebdd5,0xbbc93e00,0x3df7bd09,0xbdefbd38,0x3ded3d44,0xbd84bddc,0xbda73dc2,0x3dfabce0,0xbdfb3cc8,0x3de73d5b,0x3c7bbdfe,0xbdb13db9,
0xbdffbc49,0x3dbebdac,0xbdeabd4f,0x3d213df3,0x3cc8bdfb,0xbddc3d84,0x3dd13d93,0xbc7bbdfe,0xbd443ded,0x3df1bd2c,0xbdb1bdb9,0xbc173dff,0x3d8ebdd5,0xbdfd3c96,0x3d893dd8,0x3d09bdf7,
0xbde2bd71,0x3ddcbd84,0xbddfbd7c,0x3b493e00,0x3dd5bd8e,0xbde7bd5b,0x3c173dff,0x3dd1bd93,0xbdedbd44,0x3c963dfd,0x3dcabd9d,0xbdefbd38,0x3cc83dfb,0x3dbebdac,0xbdf3bd21,0x3ce03dfa,
0xbda2bdc6,0x3df1bd2c,0xbdd1bd93,0xbd093df7,0x3dfb3cc8,0xbc96bdfd,0xbdb93db1,0x3de53d66,0x3d44bded,0xbe00bbc9,0x3d893dd8,0x3d9dbdca,0xbdd5bd8e,0xbcf93df8,0x3defbd38,0xbda7bdc2,
0xbd15bdf5,0x3dfdbc96,0xbdc2bda7,0xbd893dd8,0x3d8e3dd5,0x3dbebdac,0xbdfebc7b,0x3b493e00,0x3ded3d44,0x3cf9bdf8,0xbde53d66,0x3d933dd1,0x3dfbbcc8,0xbd2cbdf1,0xbd7c3ddf,0x3def3d38,
0x3c49bdff,0x3e003bc9,0xbdb1bdb9,0xbdc23da7,0xbcc83dfb,0x3df83cf9,0xbd89bdd8,0xbddf3d7c,0xbd443ded,0x3de73d5b,0xbd38bdef,0xbdf33d21,0xbd8e3dd5,0x3dce3d98,0xbcafbdfc,0xbdfe3c7b,
0x3d71bde2,0x3df83cf9,0xbd9dbdca,0xbdea3d4f,0xbdd53d8e,0x3d2c3df1,0x3d21bdf3,0xbdd8bd89,0xbdedbd44,0xbd983dce,0x3df7bd09,0xbb49be00,0xbcc8bdfb,0xbe00bbc9,0x3dc23da7,0x3dd1bd93,
0x3dc6bda2,0x3de73d5b,0xbd89bdd8,0xbdfe3c7b,0xbdfbbcc8,0xbd983dce,0x3defbd38,0x3c17bdff,0x3d44bded,0xbdacbdbe,0x3caf3dfc,0x3df73d09,0x3dd53d8e,0x3ddcbd84,0xbe00bb49,0xbd663de5,
0x3df5bd15,0x3dce3d98,0xbd66bde5,0xbdfcbcaf,0xbd8ebdd5,0xbe00bbc9,0x3ddf3d7c,0x3deabd4f,0x3ded3d44,0x3ddcbd84,0xbdff3c17,0xbd893dd8,0xbdfb3cc8,0xbd5b3de7,0x3dcabd9d,0xbb49be00,
0x3dff3c49,0x3dac3dbe,0xbd38bdef,0xbde5bd66,0x3cc8bdfb,0xbd84bddc,0x3caf3dfc,0x3dca3d9d,0xbd443ded,0x3d2c3df1,0x3b49be00,0xbda7bdc2,0x3d8ebdd5,0xbc96bdfd,0xbce03dfa,0x3d7c3ddf,
0x3de23d71,0x3d843ddc,0xbd09bdf7,0xbdb9bdb1,0x3dd5bd8e,0x3d5bbde7,0xbda73dc2,0xbcaf3dfc,0xbdedbd44,0xbdfd3c96,0x3dfe3c7b,0x3deabd4f,0x3cc83dfb,0x3dac3dbe,0xbd66bde5,0xbdd8bd89,
0x3da23dc6,0x3d2c3df1,0xbcafbdfc,0xbd7cbddf,0x3dfb3cc8,0x3dfdbc96,0xbe00bb49,0xbdf33d21,0x3d44bded,0x3bc9be00,0xbce03dfa,0x3c7b3dfe,0xbdd5bd8e,0xbdf8bcf9,0x3dea3d4f,0x3dff3c17,
0x3d153df5,0x3c963dfd,0xbc17bdff,0xbce0bdfa,0x3d8e3dd5,0x3dac3dbe,0xbd9dbdca,0xbdb9bdb1,0x3ded3d44,0x3df83cf9,0xbdf3bd21,0xbdfcbcaf,0x3dfbbcc8,0x3df1bd2c,0xbdf73d09,0xbdea3d4f,
0xbdb53d80,0xbdbe3dac,0xbdb93db1,0xbdc23da7,0xbd153df5,0xbddc3d84,0xbdd83d89,0xbddf3d7c,0xbd713de2,0xbdf13d2c,0xbdef3d38,0xbdf33d21,0xbda23dc6,0xbdfd3c96,0xbdfc3caf,0xbdfe3c7b,
0x3db53d80,0x3ddcbd84,0x3dcabd9d,0x3deabd4f,0xbdff3c49,0x3de73d5b,0x3df33d21,0x3dd83d89,0xbda2bdc6,0x3c963dfd,0x3d093df7,0x3b493e00,0x3d15bdf5,0xbdbe3dac,0xbda73dc2,0xbdd13d93,
0xbdb53d80,0xbdf13d2c,0xbdd83d89,0xbdfe3c7b,0xbd71bde2,0xbc96bdfd,0xbd38bdef,0x3c17bdff,0x3df5bd15,0x3e003bc9,0x3dfcbcaf,0x3df73d09,0x3c493dff,0xbcf93df8,0xbb493e00,0xbd663de5,
0x3db53d80,0x3dfdbc96,0x3de5bd66,0x3dfc3caf,0x3da2bdc6,0xbdbe3dac,0xbd7c3ddf,0xbdea3d4f,0xbc493dff,0x3cf9bdf8,0xbc17bdff,0x3d89bdd8,0xbd71bde2,0x3d2c3df1,0x3d9d3dca,0x3b493e00,
0xbdb53d80,0xbe00bbc9,0xbdef3d38,0xbde5bd66,0x3df53d15,0x3df83cf9,0x3dfcbcaf,0x3dca3d9d,0xbde2bd71,0xbde7bd5b,0xbe00bb49,0xbda7bdc2,0x3dc63da2,0x3dce3d98,0x3dfa3ce0,0x3d7c3ddf,
0x3db53d80,0x3df83cf9,0x3df7bd09,0x3db93db1,0x3c493dff,0xbd2cbdf1,0xbdc2bda7,0x3cafbdfc,0x3dc6bda2,0xbd983dce,0xbc7b3dfe,0xbdea3d4f,0xbdf5bd15,0x3e003bc9,0x3de5bd66,0x3dd83d89,
0xbdb53d80,0xbde7bd5b,0xbdfc3caf,0xbd7cbddf,0xbde23d71,0xbd983dce,0xbb493e00,0xbdf33d21,0x3d153df5,0x3dac3dbe,0x3dfa3ce0,0x3c7b3dfe,0x3dffbc49,0x3ddcbd84,0x3d4fbdea,0x3dff3c17,
0x3db53d80,0x3dce3d98,0x3dffbc17,0x3ce03dfa,0xbdc6bda2,0x3e003bc9,0x3dcabd9d,0x3db93db1,0xbdffbc49,0x3ddcbd84,0x3d21bdf3,0x3dfc3caf,0xbde23d71,0x3d5bbde7,0xbd09bdf7,0x3deabd4f,
0xbdb53d80,0xbdacbdbe,0xbe00bb49,0x3c17bdff,0x3d15bdf5,0xbd84bddc,0xbdfabce0,0x3d09bdf7,0x3d71bde2,0xbd2cbdf1,0xbdeabd4f,0x3d66bde5,0x3da2bdc6,0xbc96bdfd,0xbdd1bd93,0x3d9dbdca,
0x3db53d80,0x3d843ddc,0x3dfe3c7b,0xbd383def,0x3dffbc49,0xbd5b3de7,0x3d663de5,0xbdfa3ce0,0x3da23dc6,0xbdfd3c96,0xbd7c3ddf,0xbdb9bdb1,0xbd153df5,0xbdacbdbe,0xbdff3c17,0x3cafbdfc,
0xbdb53d80,0xbd2cbdf1,0xbdfabce0,0x3d9dbdca,0x3d713de2,0x3dfdbc96,0x3d4fbdea,0x3da73dc2,0xbdf53d15,0xbbc93e00,0x3dd13d93,0xbddf3d7c,0xbc49bdff,0xbdf8bcf9,0xbdb93db1,0xbd21bdf3,
0x3db53d80,0x3c963dfd,0x3df33d21,0xbdd13d93,0xbda23dc6,0xbdacbdbe,0xbdf73d09,0x3d38bdef,0x3c49bdff,0x3df83cf9,0x3da7bdc2,0x3ce03dfa,0x3d713de2,0xbdf13d2c,0xbc7b3dfe,0xbdb9bdb1,
0xbdb53d80,0x3bc9be00,0xbdeabd4f,0x3df3bd21,0xbdf5bd15,0xbcf93df8,0x3dd13d93,0xbdfe3c7b,0x3de23d71,0x3d5bbde7,0xbdb1bdb9,0x3dff3c17,0xbdc6bda2,0xbd983dce,0x3d893dd8,0xbdf7bd09,
0x3db53d80,0xbcf93df8,0x3ddf3d7c,0xbe003b49,0xbc49bdff,0x3df1bd2c,0xbc17bdff,0x3d933dd1,0xbdc63da2,0xbdcebd98,0xbdca3d9d,0x3d38bdef,0x3df53d15,0xbbc93e00,0x3df33d21,0xbdfa3ce0,
0xbdb53d80,0x3d5bbde7,0xbdd1bd93,0x3df73d09,0x3de2bd71,0xbdcebd98,0xbdb93db1,0x3d66bde5,0xbd15bdf5,0xbdbe3dac,0x3d893dd8,0xbdcabd9d,0xbdff3c49,0x3d843ddc,0x3defbd38,0xbdc23da7,
0x3db53d80,0xbd983dce,0x3dc23da7,0xbdd8bd89,0x3dc63da2,0xbbc93e00,0x3dfe3c7b,0xbe003b49,0x3dff3c49,0x3d843ddc,0x3de5bd66,0xbdd13d93,0x3de2bd71,0x3de73d5b,0x3d7cbddf,0xbd383def,
0xbdb53d80,0x3dbebdac,0xbdb1bdb9,0x3da73dc2,0xbd153df5,0x3ddcbd84,0xbd89bdd8,0x3d7c3ddf,0xbd713de2,0x3df1bd2c,0xbd38bdef,0x3d213df3,0xbda23dc6,0x3dfdbc96,0xbcafbdfc,0x3c7b3dfe,
0x3db53d80,0xbddc3d84,0x3d9d3dca,0xbd4fbdea,0xbdff3c49,0xbde7bd5b,0xbd213df3,0x3d89bdd8,0xbda2bdc6,0xbc96bdfd,0xbdf73d09,0x3e00bb49,0x3d15bdf5,0x3dbebdac,0xbdc2bda7,0x3d933dd1,
0xbdb53d80,0x3df1bd2c,0xbd89bdd8,0x3c7b3dfe,0xbd71bde2,0x3c963dfd,0x3defbd38,0xbdffbc17,0x3df5bd15,0xbe00bbc9,0x3caf3dfc,0x3d09bdf7,0x3c493dff,0x3cf9bdf8,0xbe00bb49,0x3de53d66,
0x3db53d80,0xbdfd3c96,0x3d663de5,0x3cafbdfc,0x3da2bdc6,0x3dbebdac,0xbddfbd7c,0x3d4f3dea,0xbc493dff,0xbcf93df8,0x3dffbc17,0xbdd8bd89,0xbd71bde2,0xbd2cbdf1,0xbdca3d9d,0x3e00bb49,
0xbdb53d80,0x3e003bc9,0xbd38bdef,0xbd663de5,0x3df53d15,0xbdf8bcf9,0x3caf3dfc,0x3d9dbdca,0xbde2bd71,0x3de73d5b,0x3b49be00,0xbdc23da7,0x3dc63da2,0xbdcebd98,0xbce03dfa,0x3ddfbd7c,
0x3db53d80,0xbdf8bcf9,0x3d093df7,0x3db1bdb9,0x3c493dff,0x3d2c3df1,0x3da7bdc2,0xbdfcbcaf,0x3dc6bda2,0x3d98bdce,0xbdfebc7b,0x3d4f3dea,0xbdf5bd15,0xbe00bbc9,0x3d663de5,0x3d89bdd8,
0xbdb53d80,0x3de73d5b,0xbcafbdfc,0xbddf3d7c,0xbde23d71,0x3d98bdce,0xbe00bb49,0x3d213df3,0x3d153df5,0xbdacbdbe,0xbce03dfa,0x3dfebc7b,0x3dffbc49,0xbddc3d84,0x3dea3d4f,0x3c17bdff,
0x3db53d80,0xbdcebd98,0x3c173dff,0x3dfabce0,0xbdc6bda2,0xbe00bbc9,0x3d9d3dca,0x3db1bdb9,0xbdffbc49,0xbddc3d84,0x3df33d21,0x3cafbdfc,0xbde23d71,0xbd5b3de7,0x3df7bd09,0xbd4fbdea,
0xbdb53d80,0x3dac3dbe,0x3b49be00,0xbdffbc17,0x3d15bdf5,0x3d843ddc,0x3ce0bdfa,0xbdf7bd09,0x3d71bde2,0x3d2c3df1,0x3d4fbdea,0xbde5bd66,0x3da2bdc6,0x3c963dfd,0x3d93bdd1,0xbdcabd9d,
0x3db53d80,0xbd84bddc,0xbc7b3dfe,0x3def3d38,0x3dffbc49,0x3d5bbde7,0xbde53d66,0x3ce03dfa,0x3da23dc6,0x3dfdbc96,0xbddfbd7c,0xbdb13db9,0xbd153df5,0x3dac3dbe,0xbc17bdff,0xbdfcbcaf,
0xbdb53d80,0x3d2c3df1,0x3ce0bdfa,0xbdcabd9d,0x3d713de2,0xbdfd3c96,0x3dea3d4f,0x3dc2bda7,0xbdf53d15,0x3bc9be00,0xbd933dd1,0x3d7c3ddf,0xbc49bdff,0x3df83cf9,0xbdb1bdb9,0xbdf33d21,
0x3db53d80,0xbc96bdfd,0xbd213df3,0x3d933dd1,0xbda23dc6,0x3dac3dbe,0xbd09bdf7,0xbdefbd38,0x3c49bdff,0xbdf8bcf9,0x3dc23da7,0x3dfabce0,0x3d713de2,0x3df1bd2c,0xbdfebc7b,0xbdb13db9,
0xbdb53d80,0xbbc93e00,0x3d4fbdea,0xbd21bdf3,0xbdf5bd15,0x3cf9bdf8,0xbd933dd1,0x3c7b3dfe,0x3de23d71,0xbd5b3de7,0x3db9bdb1,0x3c17bdff,0xbdc6bda2,0x3d98bdce,0xbdd83d89,0xbd093df7,
0x3db53d80,0x3cf9bdf8,0xbd7c3ddf,0x3b493e00,0xbc49bdff,0xbdf13d2c,0x3dffbc17,0x3dd1bd93,0xbdc63da2,0x3dce3d98,0xbd9dbdca,0xbdefbd38,0x3df53d15,0x3bc9be00,0xbd213df3,0x3ce03dfa,
0xbdb53d80,0xbd5b3de7,0x3d93bdd1,0x3d09bdf7,0x3de2bd71,0x3dce3d98,0xbdb1bdb9,0xbde5bd66,0xbd15bdf5,0x3dbebdac,0xbdd83d89,0xbd9d3dca,0xbdff3c49,0xbd84bddc,0x3d383def,0x3da73dc2,
0x3db53d80,0x3d98bdce,0xbda73dc2,0xbd893dd8,0x3dc63da2,0x3bc9be00,0xbc7b3dfe,0x3b493e00,0x3dff3c49,0xbd84bddc,0x3d663de5,0x3d933dd1,0x3de2bd71,0xbde7bd5b,0x3ddf3d7c,0x3def3d38,
0xbcc83dfb,0xbc493dff,0xbbc93e00,0xbc963dfd,0xbd443ded,0xbd713de2,0xbd5b3de7,0xbd843ddc,0xbdb53db5,0xbdc63da2,0xbdbe3dac,0xbdce3d98,0xbded3d44,0xbdf53d15,0xbdf13d2c,0xbdf83cf9,
0xbd8e3dd5,0xbd153df5,0xbc963dfd,0xbd5b3de7,0xbded3d44,0xbdff3c49,0xbdf83cf9,0xbe00bbc9,0xbdb5bdb5,0xbd71bde2,0xbd98bdce,0xbd2cbdf1,0x3d44bded,0x3da2bdc6,0x3d84bddc,0x3dbebdac,
0xbdd53d8e,0xbd713de2,0xbcf93df8,0xbdac3dbe,0xbdedbd44,0xbda2bdc6,0xbdcebd98,0xbd5bbde7,0x3db5bdb5,0x3df5bd15,0x3ddcbd84,0x3e00bbc9,0x3d443ded,0xbc493dff,0x3c963dfd,0xbd2c3df1,
0xbdfb3cc8,0xbda23dc6,0xbd2c3df1,0xbddc3d84,0xbd44bded,0x3d15bdf5,0xbbc9be00,0x3d98bdce,0x3db53db5,0x3c493dff,0x3d5b3de7,0xbcf93df8,0xbdedbd44,0xbd71bde2,0xbdbebdac,0xbc96bdfd,
0xbdfbbcc8,0xbdc63da2,0xbd5b3de7,0xbdf83cf9,0x3d44bded,0x3df5bd15,0x3dbebdac,0x3dfd3c96,0xbdb53db5,0xbdffbc49,0xbdf13d2c,0xbddcbd84,0x3dedbd44,0x3de23d71,0x3e003bc9,0x3d983dce,
0xbdd5bd8e,0xbde23d71,0xbd843ddc,0xbe00bbc9,0x3dedbd44,0x3dc63da2,0x3dfd3c96,0x3d2c3df1,0xbdb5bdb5,0x3d15bdf5,0xbcf9bdf8,0x3dbebdac,0xbd443ded,0xbdff3c49,0xbdce3d98,0xbde7bd5b,
0xbd8ebdd5,0xbdf53d15,0xbd983dce,0xbdf1bd2c,0x3ded3d44,0xbc493dff,0x3d843ddc,0xbdac3dbe,0x3db5bdb5,0x3de23d71,0x3dfdbc96,0x3d5b3de7,0xbd44bded,0x3dc6bda2,0x3cf9bdf8,0x3e00bbc9,
0xbcc8bdfb,0xbdff3c49,0xbdac3dbe,0xbdcebd98,0x3d443ded,0xbde23d71,0xbd2c3df1,0xbdf8bcf9,0x3db53db5,0xbda23dc6,0x3bc93e00,0xbdfd3c96,0x3ded3d44,0xbd153df5,0x3d5b3de7,0xbddc3d84,
0x3cc8bdfb,0xbdffbc49,0xbdbe3dac,0xbd98bdce,0xbd443ded,0xbde2bd71,0xbdf13d2c,0xbcf9bdf8,0xbdb53db5,0xbda2bdc6,0xbe00bbc9,0x3c96bdfd,0xbded3d44,0xbd15bdf5,0xbde7bd5b,0x3d84bddc,
0x3d8ebdd5,0xbdf5bd15,0xbdce3d98,0xbd2cbdf1,0xbded3d44,0xbc49bdff,0xbddcbd84,0x3dbebdac,0xbdb5bdb5,0x3de2bd71,0x3c96bdfd,0x3de73d5b,0x3d44bded,0x3dc63da2,0x3df8bcf9,0xbbc93e00,
0x3dd5bd8e,0xbde2bd71,0xbddc3d84,0xbbc9be00,0xbdedbd44,0x3dc6bda2,0xbc96bdfd,0x3df13d2c,0x3db5bdb5,0x3d153df5,0x3df83cf9,0xbdac3dbe,0x3d443ded,0xbdffbc49,0xbd983dce,0xbd5bbde7,
0x3dfbbcc8,0xbdc6bda2,0xbde73d5b,0x3cf9bdf8,0xbd44bded,0x3df53d15,0x3dacbdbe,0x3c963dfd,0x3db53db5,0xbdff3c49,0xbd2c3df1,0xbd84bddc,0xbdedbd44,0x3de2bd71,0xbbc9be00,0x3dce3d98,
0x3dfb3cc8,0xbda2bdc6,0xbdf13d2c,0x3d84bddc,0x3d44bded,0x3d153df5,0x3e003bc9,0xbdce3d98,0xbdb53db5,0x3c49bdff,0xbde7bd5b,0x3df8bcf9,0x3dedbd44,0xbd713de2,0x3dac3dbe,0xbdfdbc96,
0x3dd53d8e,0xbd71bde2,0xbdf83cf9,0x3dbebdac,0x3dedbd44,0xbda23dc6,0x3d983dce,0xbde7bd5b,0xbdb5bdb5,0x3df53d15,0x3d84bddc,0xbbc93e00,0xbd443ded,0xbc49bdff,0xbdfdbc96,0x3df1bd2c,
0x3d8e3dd5,0xbd15bdf5,0xbdfd3c96,0x3de7bd5b,0x3ded3d44,0xbdffbc49,0xbcf93df8,0xbbc9be00,0x3db5bdb5,0xbd713de2,0x3dce3d98,0xbdf1bd2c,0xbd44bded,0x3da23dc6,0x3ddcbd84,0xbdac3dbe,
0x3cc83dfb,0xbc49bdff,0xbe003bc9,0x3dfdbc96,0x3d443ded,0xbd71bde2,0xbde73d5b,0x3ddcbd84,0x3db53db5,0xbdc6bda2,0xbdac3dbe,0x3d98bdce,0x3ded3d44,0xbdf5bd15,0xbd2c3df1,0x3cf9bdf8,
0xbcc83dfb,0x3c49bdff,0xbe00bbc9,0x3dfd3c96,0xbd443ded,0x3d71bde2,0xbde7bd5b,0x3ddc3d84,0xbdb53db5,0x3dc6bda2,0xbdacbdbe,0x3d983dce,0xbded3d44,0x3df5bd15,0xbd2cbdf1,0x3cf93df8,
0xbd8e3dd5,0x3d15bdf5,0xbdfdbc96,0x3de73d5b,0xbded3d44,0x3dffbc49,0xbcf9bdf8,0xbbc93e00,0xbdb5bdb5,0x3d713de2,0x3dcebd98,0xbdf13d2c,0x3d44bded,0xbda23dc6,0x3ddc3d84,0xbdacbdbe,
0xbdd53d8e,0x3d71bde2,0xbdf8bcf9,0x3dbe3dac,0xbdedbd44,0x3da23dc6,0x3d98bdce,0xbde73d5b,0x3db5bdb5,0xbdf53d15,0x3d843ddc,0xbbc9be00,0x3d443ded,0x3c49bdff,0xbdfd3c96,0x3df13d2c,
0xbdfb3cc8,0x3da2bdc6,0xbdf1bd2c,0x3d843ddc,0xbd44bded,0xbd153df5,0x3e00bbc9,0xbdcebd98,0x3db53db5,0xbc49bdff,0xbde73d5b,0x3df83cf9,0xbdedbd44,0x3d713de2,0x3dacbdbe,0xbdfd3c96,
0xbdfbbcc8,0x3dc6bda2,0xbde7bd5b,0x3cf93df8,0x3d44bded,0xbdf53d15,0x3dac3dbe,0x3c96bdfd,0xbdb53db5,0x3dff3c49,0xbd2cbdf1,0xbd843ddc,0x3dedbd44,0xbde2bd71,0xbbc93e00,0x3dcebd98,
0xbdd5bd8e,0x3de2bd71,0xbddcbd84,0xbbc93e00,0x3dedbd44,0xbdc6bda2,0xbc963dfd,0x3df1bd2c,0xbdb5bdb5,0xbd153df5,0x3df8bcf9,0xbdacbdbe,0xbd443ded,0x3dffbc49,0xbd98bdce,0xbd5b3de7,
0xbd8ebdd5,0x3df5bd15,0xbdcebd98,0xbd2c3df1,0x3ded3d44,0x3c49bdff,0xbddc3d84,0x3dbe3dac,0x3db5bdb5,0xbde2bd71,0x3c963dfd,0x3de7bd5b,0xbd44bded,0xbdc63da2,0x3df83cf9,0xbbc9be00,
0xbcc8bdfb,0x3dffbc49,0xbdbebdac,0xbd983dce,0x3d443ded,0x3de2bd71,0xbdf1bd2c,0xbcf93df8,0x3db53db5,0x3da2bdc6,0xbe003bc9,0x3c963dfd,0x3ded3d44,0x3d15bdf5,0xbde73d5b,0x3d843ddc,
0x3cc8bdfb,0x3dff3c49,0xbdacbdbe,0xbdce3d98,0xbd443ded,0x3de23d71,0xbd2cbdf1,0xbdf83cf9,0xbdb53db5,0x3da23dc6,0x3bc9be00,0xbdfdbc96,0xbded3d44,0x3d153df5,0x3d5bbde7,0xbddcbd84,
0x3d8ebdd5,0x3df53d15,0xbd98bdce,0xbdf13d2c,0xbded3d44,0x3c493dff,0x3d84bddc,0xbdacbdbe,0xbdb5bdb5,0xbde23d71,0x3dfd3c96,0x3d5bbde7,0x3d44bded,0xbdc6bda2,0x3cf93df8,0x3e003bc9,
0x3dd5bd8e,0x3de23d71,0xbd84bddc,0xbe003bc9,0xbdedbd44,0xbdc63da2,0x3dfdbc96,0x3d2cbdf1,0x3db5bdb5,0xbd15bdf5,0xbcf93df8,0x3dbe3dac,0x3d443ded,0x3dff3c49,0xbdcebd98,0xbde73d5b,
0x3dfbbcc8,0x3dc63da2,0xbd5bbde7,0xbdf8bcf9,0xbd44bded,0xbdf5bd15,0x3dbe3dac,0x3dfdbc96,0x3db53db5,0x3dffbc49,0xbdf1bd2c,0xbddc3d84,0xbdedbd44,0xbde23d71,0x3e00bbc9,0x3d98bdce,
0x3dfb3cc8,0x3da23dc6,0xbd2cbdf1,0xbddcbd84,0x3d44bded,0xbd15bdf5,0xbbc93e00,0x3d983dce,0xbdb53db5,0xbc493dff,0x3d5bbde7,0xbcf9bdf8,0x3dedbd44,0x3d71bde2,0xbdbe3dac,0xbc963dfd,
0x3dd53d8e,0x3d713de2,0xbcf9bdf8,0xbdacbdbe,0x3dedbd44,0x3da2bdc6,0xbdce3d98,0xbd5b3de7,0xbdb5bdb5,0xbdf5bd15,0x3ddc3d84,0x3e003bc9,0xbd443ded,0x3c493dff,0x3c96bdfd,0xbd2cbdf1,
0x3d8e3dd5,0x3d153df5,0xbc96bdfd,0xbd5bbde7,0x3ded3d44,0x3dff3c49,0xbdf8bcf9,0xbe003bc9,0x3db5bdb5,0x3d71bde2,0xbd983dce,0xbd2c3df1,0xbd44bded,0xbda2bdc6,0x3d843ddc,0x3dbe3dac,
0x3cc83dfb,0x3c493dff,0xbbc9be00,0xbc96bdfd,0x3d443ded,0x3d713de2,0xbd5bbde7,0xbd84bddc,0x3db53db5,0x3dc63da2,0xbdbebdac,0xbdcebd98,0x3ded3d44,0x3df53d15,0xbdf1bd2c,0xbdf8bcf9,
0xbd803d80,0xbdffbc49,0xbe00bbc9,0xbdfdbc96,0xbd8e3dd5,0xbde2bd71,0xbde7bd5b,0xbddcbd84,0xbdd53d8e,0xbda2bdc6,0xbdacbdbe,0xbd98bdce,0xbdfb3cc8,0xbd15bdf5,0xbd2cbdf1,0xbcf9bdf8,
0x3d803d80,0x3df53d15,0x3dfd3c96,0x3de73d5b,0xbdfbbcc8,0x3c493dff,0x3cf93df8,0xbbc93e00,0xbcc8bdfb,0xbde23d71,0xbdce3d98,0xbdf13d2c,0x3dd5bd8e,0xbdc6bda2,0xbddcbd84,0xbdacbdbe,
0xbd803d80,0xbde2bd71,0xbdf8bcf9,0xbdbebdac,0xbcc8bdfb,0x3dc6bda2,0x3d98bdce,0x3de7bd5b,0x3dfb3cc8,0x3d153df5,0x3d843ddc,0x3bc93e00,0xbd8e3dd5,0xbdffbc49,0xbdfd3c96,0xbdf1bd2c,
0x3d803d80,0x3dc63da2,0x3df13d2c,0x3d843ddc,0x3dd5bd8e,0xbdf5bd15,0xbe003bc9,0xbdcebd98,0xbd8e3dd5,0x3dffbc49,0x3de7bd5b,0x3df83cf9,0x3cc8bdfb,0xbde23d71,0xbdac3dbe,0xbdfd3c96,
0xbd803d80,0xbda2bdc6,0xbde7bd5b,0xbcf9bdf8,0x3dd53d8e,0x3d153df5,0x3dac3dbe,0xbc963dfd,0xbd8ebdd5,0x3c49bdff,0xbd2cbdf1,0x3d84bddc,0x3cc83dfb,0xbd713de2,0xbbc93e00,0xbdce3d98,
0x3d803d80,0x3d713de2,0x3ddc3d84,0xbbc93e00,0xbcc83dfb,0x3da2bdc6,0x3c96bdfd,0x3df1bd2c,0x3dfbbcc8,0xbdf5bd15,0xbdf83cf9,0xbdacbdbe,0xbd8ebdd5,0x3c493dff,0x3d983dce,0xbd5b3de7,
0xbd803d80,0xbd15bdf5,0xbdcebd98,0x3d2cbdf1,0xbdfb3cc8,0xbdffbc49,0xbddc3d84,0xbdbebdac,0xbcc83dfb,0xbd713de2,0x3c963dfd,0xbde73d5b,0x3dd53d8e,0x3da23dc6,0x3df83cf9,0x3bc93e00,
0x3d803d80,0x3c493dff,0x3dbe3dac,0xbd983dce,0xbd8ebdd5,0x3d713de2,0x3df13d2c,0xbcf93df8,0xbdd5bd8e,0x3dc63da2,0x3e00bbc9,0x3c963dfd,0xbdfbbcc8,0x3df53d15,0x3de7bd5b,0x3d843ddc,
0xbd803d80,0x3c49bdff,0xbdacbdbe,0x3dcebd98,0x3d8ebdd5,0x3d71bde2,0xbd2cbdf1,0x3df8bcf9,0x3dd5bd8e,0x3dc6bda2,0x3bc9be00,0x3dfd3c96,0x3dfbbcc8,0x3df5bd15,0x3d5bbde7,0x3ddc3d84,
0x3d803d80,0xbd153df5,0x3d983dce,0xbdf13d2c,0x3dfb3cc8,0xbdff3c49,0xbd843ddc,0xbdacbdbe,0x3cc83dfb,0xbd71bde2,0xbdfdbc96,0x3d5bbde7,0xbdd53d8e,0x3da2bdc6,0xbcf9bdf8,0x3e003bc9,
0xbd803d80,0x3d71bde2,0xbd84bddc,0x3e00bbc9,0x3cc83dfb,0x3da23dc6,0x3dfdbc96,0xbd2c3df1,0xbdfbbcc8,0xbdf53d15,0xbcf93df8,0xbdbebdac,0x3d8ebdd5,0x3c49bdff,0xbdcebd98,0x3de7bd5b,
0x3d803d80,0xbda23dc6,0x3d5b3de7,0xbdf8bcf9,0xbdd53d8e,0x3d15bdf5,0xbdbebdac,0x3dfdbc96,0x3d8ebdd5,0x3c493dff,0x3df13d2c,0xbddc3d84,0xbcc83dfb,0xbd71bde2,0xbe003bc9,0x3d98bdce,
0xbd803d80,0x3dc6bda2,0xbd2cbdf1,0x3ddc3d84,0xbdd5bd8e,0xbdf53d15,0xbbc93e00,0xbd98bdce,0x3d8e3dd5,0x3dff3c49,0x3d5bbde7,0x3cf93df8,0xbcc8bdfb,0xbde2bd71,0xbdbe3dac,0x3c96bdfd,
0x3d803d80,0xbde23d71,0x3cf93df8,0xbdacbdbe,0x3cc8bdfb,0x3dc63da2,0x3dcebd98,0xbd5b3de7,0xbdfb3cc8,0x3d15bdf5,0xbddcbd84,0x3e003bc9,0x3d8e3dd5,0xbdff3c49,0xbc963dfd,0xbd2cbdf1,
0xbd803d80,0x3df5bd15,0xbc96bdfd,0x3d5b3de7,0x3dfbbcc8,0x3c49bdff,0xbdf8bcf9,0x3e00bbc9,0x3cc8bdfb,0xbde2bd71,0xbd983dce,0x3d2cbdf1,0xbdd5bd8e,0xbdc63da2,0x3d843ddc,0xbdbebdac,
0x3d803d80,0xbdff3c49,0x3bc93e00,0xbc96bdfd,0x3d8e3dd5,0xbde23d71,0x3d5b3de7,0xbd84bddc,0x3dd53d8e,0xbda23dc6,0x3dbe3dac,0xbdcebd98,0x3dfb3cc8,0xbd153df5,0x3df13d2c,0xbdf8bcf9,
0xbd803d80,0x3dff3c49,0x3bc9be00,0xbc963dfd,0xbd8e3dd5,0x3de23d71,0x3d5bbde7,0xbd843ddc,0xbdd53d8e,0x3da23dc6,0x3dbebdac,0xbdce3d98,0xbdfb3cc8,0x3d153df5,0x3df1bd2c,0xbdf83cf9,
0x3d803d80,0xbdf5bd15,0xbc963dfd,0x3d5bbde7,0xbdfbbcc8,0xbc49bdff,0xbdf83cf9,0x3e003bc9,0xbcc8bdfb,0x3de2bd71,0xbd98bdce,0x3d2c3df1,0x3dd5bd8e,0x3dc63da2,0x3d84bddc,0xbdbe3dac,
0xbd803d80,0x3de23d71,0x3cf9bdf8,0xbdac3dbe,0xbcc8bdfb,0xbdc63da2,0x3dce3d98,0xbd5bbde7,0x3dfb3cc8,0xbd15bdf5,0xbddc3d84,0x3e00bbc9,0xbd8e3dd5,0x3dff3c49,0xbc96bdfd,0xbd2c3df1,
0x3d803d80,0xbdc6bda2,0xbd2c3df1,0x3ddcbd84,0x3dd5bd8e,0x3df53d15,0xbbc9be00,0xbd983dce,0xbd8e3dd5,0xbdff3c49,0x3d5b3de7,0x3cf9bdf8,0x3cc8bdfb,0x3de2bd71,0xbdbebdac,0x3c963dfd,
0xbd803d80,0x3da23dc6,0x3d5bbde7,0xbdf83cf9,0x3dd53d8e,0xbd15bdf5,0xbdbe3dac,0x3dfd3c96,0xbd8ebdd5,0xbc493dff,0x3df1bd2c,0xbddcbd84,0x3cc83dfb,0x3d71bde2,0xbe00bbc9,0x3d983dce,
0x3d803d80,0xbd71bde2,0xbd843ddc,0x3e003bc9,0xbcc83dfb,0xbda23dc6,0x3dfd3c96,0xbd2cbdf1,0x3dfbbcc8,0x3df53d15,0xbcf9bdf8,0xbdbe3dac,0xbd8ebdd5,0xbc49bdff,0xbdce3d98,0x3de73d5b,
0xbd803d80,0x3d153df5,0x3d98bdce,0xbdf1bd2c,0xbdfb3cc8,0x3dff3c49,0xbd84bddc,0xbdac3dbe,0xbcc83dfb,0x3d71bde2,0xbdfd3c96,0x3d5b3de7,0x3dd53d8e,0xbda2bdc6,0xbcf93df8,0x3e00bbc9,
0x3d803d80,0xbc49bdff,0xbdac3dbe,0x3dce3d98,0xbd8ebdd5,0xbd71bde2,0xbd2c3df1,0x3df83cf9,0xbdd5bd8e,0xbdc6bda2,0x3bc93e00,0x3dfdbc96,0xbdfbbcc8,0xbdf5bd15,0x3d5b3de7,0x3ddcbd84,
0xbd803d80,0xbc493dff,0x3dbebdac,0xbd98bdce,0x3d8ebdd5,0xbd713de2,0x3df1bd2c,0xbcf9bdf8,0x3dd5bd8e,0xbdc63da2,0x3e003bc9,0x3c96bdfd,0x3dfbbcc8,0xbdf53d15,0x3de73d5b,0x3d84bddc,
0x3d803d80,0x3d15bdf5,0xbdce3d98,0x3d2c3df1,0x3dfb3cc8,0x3dffbc49,0xbddcbd84,0xbdbe3dac,0x3cc83dfb,0x3d713de2,0x3c96bdfd,0xbde7bd5b,0xbdd53d8e,0xbda23dc6,0x3df8bcf9,0x3bc9be00,
0xbd803d80,0xbd713de2,0x3ddcbd84,0xbbc9be00,0x3cc83dfb,0xbda2bdc6,0x3c963dfd,0x3df13d2c,0xbdfbbcc8,0x3df5bd15,0xbdf8bcf9,0xbdac3dbe,0x3d8ebdd5,0xbc493dff,0x3d98bdce,0xbd5bbde7,
0x3d803d80,0x3da2bdc6,0xbde73d5b,0xbcf93df8,0xbdd53d8e,0xbd153df5,0x3dacbdbe,0xbc96bdfd,0x3d8ebdd5,0xbc49bdff,0xbd2c3df1,0x3d843ddc,0xbcc83dfb,0x3d713de2,0xbbc9be00,0xbdcebd98,
0xbd803d80,0xbdc63da2,0x3df1bd2c,0x3d84bddc,0xbdd5bd8e,0x3df5bd15,0xbe00bbc9,0xbdce3d98,0x3d8e3dd5,0xbdffbc49,0x3de73d5b,0x3df8bcf9,0xbcc8bdfb,0x3de23d71,0xbdacbdbe,0xbdfdbc96,
0x3d803d80,0x3de2bd71,0xbdf83cf9,0xbdbe3dac,0x3cc8bdfb,0xbdc6bda2,0x3d983dce,0x3de73d5b,0xbdfb3cc8,0xbd153df5,0x3d84bddc,0x3bc9be00,0x3d8e3dd5,0x3dffbc49,0xbdfdbc96,0xbdf13d2c,
0xbd803d80,0xbdf53d15,0x3dfdbc96,0x3de7bd5b,0x3dfbbcc8,0xbc493dff,0x3cf9bdf8,0xbbc9be00,0x3cc8bdfb,0x3de23d71,0xbdcebd98,0xbdf1bd2c,0xbdd5bd8e,0x3dc6bda2,0xbddc3d84,0xbdac3dbe,
0x3d803d80,0x3dffbc49,0xbe003bc9,0xbdfd3c96,0x3d8e3dd5,0x3de2bd71,0xbde73d5b,0xbddc3d84,0x3dd53d8e,0x3da2bdc6,0xbdac3dbe,0xbd983dce,0x3dfb3cc8,0x3d15bdf5,0xbd2c3df1,0xbcf93df8,
0xbd153df5,0xbc963dfd,0xbc173dff,0xbce03dfa,0xbd8e3dd5,0xbdac3dbe,0xbd9d3dca,0xbdb93db1,0xbded3d44,0xbdf83cf9,0xbdf33d21,0xbdfc3caf,0xbdfbbcc8,0xbdf1bd2c,0xbdf7bd09,0xbdeabd4f,
0xbda23dc6,0xbd2c3df1,0xbcaf3dfc,0xbd7c3ddf,0xbdfb3cc8,0xbdfdbc96,0xbe003b49,0xbdf3bd21,0xbd44bded,0xbbc9be00,0xbce0bdfa,0x3c7bbdfe,0x3dd5bd8e,0x3df8bcf9,0x3deabd4f,0x3dffbc17,
0xbde23d71,0xbd843ddc,0xbd093df7,0xbdb93db1,0xbdd5bd8e,0xbd5bbde7,0xbda7bdc2,0xbcafbdfc,0x3dedbd44,0x3dfd3c96,0x3dfebc7b,0x3dea3d4f,0xbcc83dfb,0xbdac3dbe,0xbd663de5,0xbdd83d89,
0xbdff3c49,0xbdac3dbe,0xbd383def,0xbde53d66,0xbcc8bdfb,0x3d84bddc,0x3cafbdfc,0x3dcabd9d,0x3d443ded,0xbd2c3df1,0x3b493e00,0xbda73dc2,0xbd8ebdd5,0x3c96bdfd,0xbce0bdfa,0x3d7cbddf,
0xbdf5bd15,0xbdce3d98,0xbd663de5,0xbdfc3caf,0x3d8ebdd5,0x3e00bbc9,0x3ddfbd7c,0x3dea3d4f,0xbded3d44,0xbddcbd84,0xbdffbc17,0xbd89bdd8,0x3dfb3cc8,0x3d5b3de7,0x3dca3d9d,0xbb493e00,
0xbdc6bda2,0xbde73d5b,0xbd893dd8,0xbdfebc7b,0x3dfbbcc8,0x3d983dce,0x3def3d38,0x3c173dff,0xbd44bded,0x3dacbdbe,0x3cafbdfc,0x3df7bd09,0xbdd53d8e,0xbddcbd84,0xbe003b49,0xbd66bde5,
0xbd71bde2,0xbdf83cf9,0xbd9d3dca,0xbdeabd4f,0x3dd53d8e,0xbd2c3df1,0x3d213df3,0xbdd83d89,0x3dedbd44,0x3d983dce,0x3df73d09,0xbb493e00,0x3cc8bdfb,0x3e00bbc9,0x3dc2bda7,0x3dd13d93,
0xbc49bdff,0xbe003bc9,0xbdb13db9,0xbdc2bda7,0x3cc83dfb,0xbdf83cf9,0xbd893dd8,0xbddfbd7c,0x3d443ded,0xbde73d5b,0xbd383def,0xbdf3bd21,0x3d8e3dd5,0xbdce3d98,0xbcaf3dfc,0xbdfebc7b,
0x3d15bdf5,0xbdfdbc96,0xbdc23da7,0xbd89bdd8,0xbd8e3dd5,0xbdbebdac,0xbdfe3c7b,0x3b49be00,0xbded3d44,0xbcf9bdf8,0xbde5bd66,0x3d93bdd1,0xbdfbbcc8,0x3d2cbdf1,0xbd7cbddf,0x3defbd38,
0x3da2bdc6,0xbdf1bd2c,0xbdd13d93,0xbd09bdf7,0xbdfb3cc8,0x3c96bdfd,0xbdb9bdb1,0x3de5bd66,0xbd44bded,0x3e00bbc9,0x3d89bdd8,0x3d9d3dca,0x3dd5bd8e,0x3cf93df8,0x3def3d38,0xbda73dc2,
0x3de2bd71,0xbddcbd84,0xbddf3d7c,0x3b49be00,0xbdd5bd8e,0x3de7bd5b,0x3c17bdff,0x3dd13d93,0x3dedbd44,0xbc963dfd,0x3dca3d9d,0xbdef3d38,0xbcc83dfb,0xbdbebdac,0xbdf33d21,0x3ce0bdfa,
0x3dffbc49,0xbdbebdac,0xbdea3d4f,0x3d21bdf3,0xbcc8bdfb,0x3ddc3d84,0x3dd1bd93,0xbc7b3dfe,0x3d443ded,0xbdf1bd2c,0xbdb13db9,0xbc17bdff,0xbd8ebdd5,0x3dfd3c96,0x3d89bdd8,0x3d093df7,
0x3df53d15,0xbd98bdce,0xbdf33d21,0x3d93bdd1,0x3d8ebdd5,0x3bc93e00,0x3df73d09,0xbdef3d38,0xbded3d44,0x3d84bddc,0xbda7bdc2,0x3dfa3ce0,0x3dfb3cc8,0xbde73d5b,0x3c7b3dfe,0xbdb1bdb9,
0x3dc63da2,0xbd5bbde7,0xbdfa3ce0,0x3dcabd9d,0x3dfbbcc8,0xbdce3d98,0x3d4f3dea,0xbdc2bda7,0xbd44bded,0x3dbe3dac,0x3dd1bd93,0xbd7c3ddf,0xbdd53d8e,0x3d84bddc,0xbdb9bdb1,0x3df33d21,
0x3d713de2,0xbcf9bdf8,0xbdfe3c7b,0x3defbd38,0x3dd53d8e,0xbdf1bd2c,0xbd663de5,0x3ce0bdfa,0x3dedbd44,0xbdce3d98,0x3d7c3ddf,0xbdb1bdb9,0x3cc8bdfb,0x3bc93e00,0x3dff3c17,0xbdfc3caf,
0x3c493dff,0xbbc9be00,0xbe003b49,0x3dffbc17,0x3cc83dfb,0xbcf9bdf8,0xbdfa3ce0,0x3df7bd09,0x3d443ded,0xbd5bbde7,0xbdea3d4f,0x3de5bd66,0x3d8e3dd5,0xbd98bdce,0xbdd13d93,0x3dcabd9d,
0xbd153df5,0x3c96bdfd,0xbdffbc17,0x3dfa3ce0,0xbd8e3dd5,0x3dacbdbe,0xbdcabd9d,0x3db13db9,0xbded3d44,0x3df8bcf9,0xbd21bdf3,0x3caf3dfc,0xbdfbbcc8,0x3df13d2c,0x3d09bdf7,0xbd4f3dea,
0xbda23dc6,0x3d2cbdf1,0xbdfcbcaf,0x3ddf3d7c,0xbdfb3cc8,0x3dfd3c96,0xbb49be00,0xbd213df3,0xbd44bded,0x3bc93e00,0x3dfabce0,0xbdfebc7b,0x3dd5bd8e,0xbdf83cf9,0x3d4f3dea,0xbc17bdff,
0xbde23d71,0x3d84bddc,0xbdf7bd09,0x3db13db9,0xbdd5bd8e,0x3d5b3de7,0x3dc2bda7,0xbdfc3caf,0x3dedbd44,0xbdfdbc96,0x3c7b3dfe,0x3d4fbdea,0xbcc83dfb,0x3dacbdbe,0xbde5bd66,0x3d893dd8,
0xbdff3c49,0x3dacbdbe,0xbdefbd38,0x3d663de5,0xbcc8bdfb,0xbd843ddc,0x3dfc3caf,0xbd9dbdca,0x3d443ded,0x3d2cbdf1,0xbe003b49,0x3dc23da7,0xbd8ebdd5,0xbc963dfd,0x3dfabce0,0xbddfbd7c,
0xbdf5bd15,0x3dcebd98,0xbde5bd66,0x3caf3dfc,0x3d8ebdd5,0xbe003bc9,0x3d7c3ddf,0x3d4fbdea,0xbded3d44,0x3ddc3d84,0x3c17bdff,0xbdd83d89,0x3dfb3cc8,0xbd5bbde7,0xbd9d3dca,0x3e003b49,
0xbdc6bda2,0x3de7bd5b,0xbdd8bd89,0xbc7b3dfe,0x3dfbbcc8,0xbd98bdce,0xbd383def,0x3dffbc17,0xbd44bded,0xbdac3dbe,0x3dfc3caf,0xbd09bdf7,0xbdd53d8e,0x3ddc3d84,0xbb49be00,0xbde53d66,
0xbd71bde2,0x3df8bcf9,0xbdcabd9d,0xbd4f3dea,0x3dd53d8e,0x3d2cbdf1,0xbdf33d21,0x3d893dd8,0x3dedbd44,0xbd98bdce,0xbd093df7,0x3e003b49,0x3cc8bdfb,0xbe003bc9,0x3da73dc2,0x3d93bdd1,
0xbc49bdff,0x3e00bbc9,0xbdb9bdb1,0xbda73dc2,0x3cc83dfb,0x3df8bcf9,0xbdd8bd89,0xbd7c3ddf,0x3d443ded,0x3de7bd5b,0xbdefbd38,0xbd213df3,0x3d8e3dd5,0x3dcebd98,0xbdfcbcaf,0xbc7b3dfe,
0x3d15bdf5,0x3dfd3c96,0xbda7bdc2,0xbdd83d89,0xbd8e3dd5,0x3dbe3dac,0xbc7bbdfe,0xbe00bb49,0xbded3d44,0x3cf93df8,0x3d66bde5,0xbdd1bd93,0xbdfbbcc8,0xbd2c3df1,0x3ddfbd7c,0xbd38bdef,
0x3da2bdc6,0x3df13d2c,0xbd93bdd1,0xbdf73d09,0xbdfb3cc8,0xbc963dfd,0x3db1bdb9,0xbd66bde5,0xbd44bded,0xbe003bc9,0x3dd83d89,0x3dcabd9d,0x3dd5bd8e,0xbcf9bdf8,0xbd383def,0x3dc23da7,
0x3de2bd71,0x3ddc3d84,0xbd7cbddf,0xbe00bb49,0xbdd5bd8e,0xbde73d5b,0x3dff3c17,0x3d93bdd1,0x3dedbd44,0x3c96bdfd,0xbd9d3dca,0x3d383def,0xbcc83dfb,0x3dbe3dac,0xbd21bdf3,0xbdfabce0,
0x3dffbc49,0x3dbe3dac,0xbd4fbdea,0xbdf3bd21,0xbcc8bdfb,0xbddcbd84,0x3d933dd1,0x3dfe3c7b,0x3d443ded,0x3df13d2c,0xbdb9bdb1,0xbdff3c17,0xbd8ebdd5,0xbdfdbc96,0x3dd83d89,0x3df7bd09,
0x3df53d15,0x3d983dce,0xbd21bdf3,0xbdd1bd93,0x3d8ebdd5,0xbbc9be00,0xbd093df7,0x3d383def,0xbded3d44,0xbd843ddc,0x3dc2bda7,0x3ce0bdfa,0x3dfb3cc8,0x3de7bd5b,0xbdfe3c7b,0xbdb93db1,
0x3dc63da2,0x3d5b3de7,0xbce0bdfa,0xbd9dbdca,0x3dfbbcc8,0x3dcebd98,0xbdea3d4f,0xbda73dc2,0xbd44bded,0xbdbebdac,0x3d933dd1,0x3ddf3d7c,0xbdd53d8e,0xbd843ddc,0x3db1bdb9,0x3d21bdf3,
0x3d713de2,0x3cf93df8,0xbc7bbdfe,0xbd38bdef,0x3dd53d8e,0x3df13d2c,0xbde5bd66,0xbdfabce0,0x3dedbd44,0x3dcebd98,0xbddf3d7c,0xbdb93db1,0x3cc8bdfb,0xbbc9be00,0xbc173dff,0x3caf3dfc,
0x3c493dff,0x3bc93e00,0xbb49be00,0xbc17bdff,0x3cc83dfb,0x3cf93df8,0xbce0bdfa,0xbd09bdf7,0x3d443ded,0x3d5b3de7,0xbd4fbdea,0xbd66bde5,0x3d8e3dd5,0x3d983dce,0xbd93bdd1,0xbd9dbdca,
0xbdb53d80,0xbd98bdce,0xbda7bdc2,0xbd89bdd8,0xbdc63da2,0xbbc9be00,0xbc7bbdfe,0x3b49be00,0xbdff3c49,0x3d84bddc,0x3d66bde5,0x3d93bdd1,0xbde2bd71,0x3de7bd5b,0x3ddfbd7c,0x3defbd38,
0x3db53d80,0x3d5b3de7,0x3d933dd1,0x3d093df7,0xbde2bd71,0xbdce3d98,0xbdb13db9,0xbde53d66,0x3d15bdf5,0xbdbebdac,0xbdd8bd89,0xbd9dbdca,0x3dff3c49,0x3d84bddc,0x3d38bdef,0x3da7bdc2,
0xbdb53d80,0xbcf9bdf8,0xbd7cbddf,0x3b49be00,0x3c49bdff,0x3df13d2c,0x3dff3c17,0x3dd13d93,0x3dc63da2,0xbdce3d98,0xbd9d3dca,0xbdef3d38,0xbdf53d15,0xbbc9be00,0xbd21bdf3,0x3ce0bdfa,
0x3db53d80,0x3bc93e00,0x3d4f3dea,0xbd213df3,0x3df5bd15,0xbcf9bdf8,0xbd93bdd1,0x3c7bbdfe,0xbde23d71,0x3d5b3de7,0x3db93db1,0x3c173dff,0x3dc6bda2,0xbd98bdce,0xbdd8bd89,0xbd09bdf7,
0xbdb53d80,0x3c96bdfd,0xbd21bdf3,0x3d93bdd1,0x3da23dc6,0xbdac3dbe,0xbd093df7,0xbdef3d38,0xbc49bdff,0x3df8bcf9,0x3dc2bda7,0x3dfa3ce0,0xbd713de2,0xbdf1bd2c,0xbdfe3c7b,0xbdb1bdb9,
0x3db53d80,0xbd2c3df1,0x3ce03dfa,0xbdca3d9d,0xbd713de2,0x3dfd3c96,0x3deabd4f,0x3dc23da7,0x3df53d15,0xbbc9be00,0xbd93bdd1,0x3d7cbddf,0x3c49bdff,0xbdf83cf9,0xbdb13db9,0xbdf3bd21,
0xbdb53d80,0x3d84bddc,0xbc7bbdfe,0x3defbd38,0xbdffbc49,0xbd5bbde7,0xbde5bd66,0x3ce0bdfa,0xbda23dc6,0xbdfdbc96,0xbddf3d7c,0xbdb1bdb9,0x3d153df5,0xbdac3dbe,0xbc173dff,0xbdfc3caf,
0x3db53d80,0xbdac3dbe,0x3b493e00,0xbdff3c17,0xbd15bdf5,0xbd843ddc,0x3ce03dfa,0xbdf73d09,0xbd71bde2,0xbd2c3df1,0x3d4f3dea,0xbde53d66,0xbda2bdc6,0xbc963dfd,0x3d933dd1,0xbdca3d9d,
0xbdb53d80,0x3dcebd98,0x3c17bdff,0x3dfa3ce0,0x3dc6bda2,0x3e00bbc9,0x3d9dbdca,0x3db13db9,0x3dffbc49,0x3ddc3d84,0x3df3bd21,0x3caf3dfc,0x3de23d71,0x3d5b3de7,0x3df73d09,0xbd4f3dea,
0x3db53d80,0xbde73d5b,0xbcaf3dfc,0xbddfbd7c,0x3de23d71,0xbd98bdce,0xbe003b49,0x3d21bdf3,0xbd153df5,0x3dacbdbe,0xbce0bdfa,0x3dfe3c7b,0xbdffbc49,0x3ddc3d84,0x3deabd4f,0x3c173dff,
0xbdb53d80,0x3df8bcf9,0x3d09bdf7,0x3db13db9,0xbc493dff,0xbd2c3df1,0x3da73dc2,0xbdfc3caf,0xbdc6bda2,0xbd98bdce,0xbdfe3c7b,0x3d4fbdea,0x3df5bd15,0x3e00bbc9,0x3d66bde5,0x3d893dd8,
0x3db53d80,0xbe003bc9,0xbd383def,0xbd66bde5,0xbdf53d15,0x3df8bcf9,0x3cafbdfc,0x3d9d3dca,0x3de2bd71,0xbde73d5b,0x3b493e00,0xbdc2bda7,0xbdc63da2,0x3dcebd98,0xbce0bdfa,0x3ddf3d7c,
0xbdb53d80,0x3dfd3c96,0x3d66bde5,0x3caf3dfc,0xbda2bdc6,0xbdbebdac,0xbddf3d7c,0x3d4fbdea,0x3c493dff,0x3cf93df8,0x3dff3c17,0xbdd83d89,0x3d71bde2,0x3d2cbdf1,0xbdcabd9d,0x3e003b49,
0x3db53d80,0xbdf1bd2c,0xbd893dd8,0x3c7bbdfe,0x3d71bde2,0xbc963dfd,0x3def3d38,0xbdff3c17,0xbdf5bd15,0x3e00bbc9,0x3cafbdfc,0x3d093df7,0xbc493dff,0xbcf9bdf8,0xbe003b49,0x3de5bd66,
0xbdb53d80,0x3ddc3d84,0x3d9dbdca,0xbd4f3dea,0x3dff3c49,0x3de7bd5b,0xbd21bdf3,0x3d893dd8,0x3da2bdc6,0x3c96bdfd,0xbdf7bd09,0x3e003b49,0xbd15bdf5,0xbdbebdac,0xbdc23da7,0x3d93bdd1,
0x3db53d80,0xbdbebdac,0xbdb13db9,0x3da7bdc2,0x3d153df5,0xbddcbd84,0xbd893dd8,0x3d7cbddf,0x3d713de2,0xbdf1bd2c,0xbd383def,0x3d21bdf3,0x3da23dc6,0xbdfdbc96,0xbcaf3dfc,0x3c7bbdfe,
0xbdb53d80,0x3d983dce,0x3dc2bda7,0xbdd83d89,0xbdc63da2,0x3bc93e00,0x3dfebc7b,0xbe00bb49,0xbdff3c49,0xbd843ddc,0x3de53d66,0xbdd1bd93,0xbde2bd71,0xbde73d5b,0x3d7c3ddf,0xbd38bdef,
0x3db53d80,0xbd5bbde7,0xbdd13d93,0x3df7bd09,0xbde2bd71,0x3dcebd98,0xbdb9bdb1,0x3d663de5,0x3d15bdf5,0x3dbe3dac,0x3d89bdd8,0xbdca3d9d,0x3dff3c49,0xbd843ddc,0x3def3d38,0xbdc2bda7,
0xbdb53d80,0x3cf93df8,0x3ddfbd7c,0xbe00bb49,0x3c49bdff,0xbdf1bd2c,0xbc173dff,0x3d93bdd1,0x3dc63da2,0x3dcebd98,0xbdcabd9d,0x3d383def,0xbdf53d15,0x3bc93e00,0x3df3bd21,0xbdfabce0,
0x3db53d80,0xbbc9be00,0xbdea3d4f,0x3df33d21,0x3df5bd15,0x3cf93df8,0x3dd1bd93,0xbdfebc7b,0xbde23d71,0xbd5bbde7,0xbdb13db9,0x3dffbc17,0x3dc6bda2,0x3d983dce,0x3d89bdd8,0xbdf73d09,
0xbdb53d80,0xbc963dfd,0x3df3bd21,0xbdd1bd93,0x3da23dc6,0x3dacbdbe,0xbdf7bd09,0x3d383def,0xbc49bdff,0xbdf83cf9,0x3da73dc2,0x3ce0bdfa,0xbd713de2,0x3df13d2c,0xbc7bbdfe,0xbdb93db1,
0x3db53d80,0x3d2cbdf1,0xbdfa3ce0,0x3d9d3dca,0xbd713de2,0xbdfdbc96,0x3d4f3dea,0x3da7bdc2,0x3df53d15,0x3bc93e00,0x3dd1bd93,0xbddfbd7c,0x3c49bdff,0x3df8bcf9,0xbdb9bdb1,0xbd213df3,
0xbdb53d80,0xbd843ddc,0x3dfebc7b,0xbd38bdef,0xbdffbc49,0x3d5b3de7,0x3d66bde5,0xbdfabce0,0xbda23dc6,0x3dfd3c96,0xbd7cbddf,0xbdb93db1,0x3d153df5,0x3dacbdbe,0xbdffbc17,0x3caf3dfc,
0x3db53d80,0x3dacbdbe,0xbe003b49,0x3c173dff,0xbd15bdf5,0x3d84bddc,0xbdfa3ce0,0x3d093df7,0xbd71bde2,0x3d2cbdf1,0xbdea3d4f,0x3d663de5,0xbda2bdc6,0x3c96bdfd,0xbdd13d93,0x3d9d3dca,
0xbdb53d80,0xbdce3d98,0x3dff3c17,0x3ce0bdfa,0x3dc6bda2,0xbe003bc9,0x3dca3d9d,0x3db9bdb1,0x3dffbc49,0xbddcbd84,0x3d213df3,0x3dfcbcaf,0x3de23d71,0xbd5bbde7,0xbd093df7,0x3dea3d4f,
0x3db53d80,0x3de7bd5b,0xbdfcbcaf,0xbd7c3ddf,0x3de23d71,0x3d983dce,0xbb49be00,0xbdf3bd21,0xbd153df5,0xbdac3dbe,0x3dfabce0,0x3c7bbdfe,0xbdffbc49,0xbddcbd84,0x3d4f3dea,0x3dffbc17,
0xbdb53d80,0xbdf83cf9,0x3df73d09,0x3db9bdb1,0xbc493dff,0x3d2cbdf1,0xbdc23da7,0x3caf3dfc,0xbdc6bda2,0x3d983dce,0xbc7bbdfe,0xbdeabd4f,0x3df5bd15,0xbe003bc9,0x3de53d66,0x3dd8bd89,
0x3db53d80,0x3e00bbc9,0xbdefbd38,0xbde53d66,0xbdf53d15,0xbdf83cf9,0x3dfc3caf,0x3dcabd9d,0x3de2bd71,0x3de7bd5b,0xbe003b49,0xbda73dc2,0xbdc63da2,0xbdce3d98,0x3dfabce0,0x3d7cbddf,
0xbdb53d80,0xbdfdbc96,0x3de53d66,0x3dfcbcaf,0xbda2bdc6,0x3dbe3dac,0xbd7cbddf,0xbdeabd4f,0x3c493dff,0xbcf9bdf8,0xbc173dff,0x3d893dd8,0x3d71bde2,0xbd2c3df1,0x3d9dbdca,0x3b49be00,
0x3db53d80,0x3df13d2c,0xbdd8bd89,0xbdfebc7b,0x3d71bde2,0x3c96bdfd,0xbd383def,0x3c173dff,0xbdf5bd15,0xbe003bc9,0x3dfc3caf,0x3df7bd09,0xbc493dff,0x3cf93df8,0xbb49be00,0xbd66bde5,
0xbdb53d80,0xbddcbd84,0x3dca3d9d,0x3dea3d4f,0x3dff3c49,0xbde73d5b,0x3df3bd21,0x3dd8bd89,0x3da2bdc6,0xbc963dfd,0x3d09bdf7,0x3b49be00,0xbd15bdf5,0x3dbe3dac,0xbda7bdc2,0xbdd1bd93,
0x3db53d80,0x3dbe3dac,0xbdb9bdb1,0xbdc2bda7,0x3d153df5,0x3ddc3d84,0xbdd8bd89,0xbddfbd7c,0x3d713de2,0x3df13d2c,0xbdefbd38,0xbdf3bd21,0x3da23dc6,0x3dfd3c96,0xbdfcbcaf,0xbdfebc7b,
0x3f800000,0x0,0x3f800000,0x0,0x3f800000,0x0,0x3f800000,0x0,0x3f800000,0x0,0x3f800000,0x0,0x3f800000,0x0,0x3f800000,0x0,
0x3f800000,0x0,0x3f7ffb11,0xbc490e90,0x3f7fec43,0xbcc90ab0,0x3f7fd397,0xbd16c32c,0x3f7fb10f,0xbd48fb30,0x3f7f84ab,0xbd7b2b74,0x3f7f4e6d,0xbd96a905,0x3f7f0e58,0xbdafb680,
0x3f800000,0x0,0x3f7fec43,0xbcc90ab0,0x3f7fb10f,0xbd48fb30,0x3f7f4e6d,0xbd96a905,0x3f7ec46d,0xbdc8bd36,0x3f7e1324,0xbdfab273,0x3f7d3aac,0xbe164083,0x3f7c3b28,0xbe2f10a2,
0x3f800000,0x0,0x3f7fd397,0xbd16c32c,0x3f7f4e6d,0xbd96a905,0x3f7e70b0,0xbde1bc2e,0x3f7d3aac,0xbe164083,0x3f7baccd,0xbe3b6ecf,0x3f79c79d,0xbe605c13,0x3f778bc5,0xbe827dc0,
0x3f800000,0x0,0x3f7fb10f,0xbd48fb30,0x3f7ec46d,0xbdc8bd36,0x3f7d3aac,0xbe164083,0x3f7b14be,0xbe47c5c2,0x3f7853f8,0xbe78cfcc,0x3f74fa0b,0xbe94a031,0x3f710908,0xbeac7cd4,
0x3f800000,0x0,0x3f7f84ab,0xbd7b2b74,0x3f7e1324,0xbdfab273,0x3f7baccd,0xbe3b6ecf,0x3f7853f8,0xbe78cfcc,0x3f740bdd,0xbe9aa086,0x3f6ed89e,0xbeb8442a,0x3f68bf3c,0xbed53641,
0x3f800000,0x0,0x3f7f4e6d,0xbd96a905,0x3f7d3aac,0xbe164083,0x3f79c79d,0xbe605c13,0x3f74fa0b,0xbe94a031,0x3f6ed89e,0xbeb8442a,0x3f676bd8,0xbedae880,0x3f5ebe05,0xbefc5d27,
0x3f800000,0x0,0x3f7f0e58,0xbdafb680,0x3f7c3b28,0xbe2f10a2,0x3f778bc5,0xbe827dc0,0x3f710908,0xbeac7cd4,0x3f68bf3c,0xbed53641,0x3f5ebe05,0xbefc5d27,0x3f531849,0xbf10d3cd,
0x3f800000,0x0,0x3f7b14be,0xbe47c5c2,0x3f6c835e,0xbec3ef15,0x3f54db31,0xbf0e39da,0x3f3504f3,0xbf3504f3,0x3f0e39da,0xbf54db31,0x3ec3ef15,0xbf6c835e,0x3e47c5c2,0xbf7b14be,
0x3f800000,0x0,0x3f7a7302,0xbe541501,0x3f6a09a7,0xbecf7bca,0x3f4f7a1f,0xbf15f6d9,0x3f2beb4a,0xbf3daef9,0x3f00e7e4,0xbf5d2d53,0x3ea09ae5,0xbf731447,0x3de1bc2e,0xbf7e70b0,
0x3f800000,0x0,0x3f79c79d,0xbe605c13,0x3f676bd8,0xbedae880,0x3f49d112,0xbf1d7fd1,0x3f226799,0xbf45e403,0x3ee63375,0xbf64aa59,0x3e78cfcc,0xbf7853f8,0x3cc90ab0,0xbf7fec43,
0x3f800000,0x0,0x3f791298,0xbe6c9a7f,0x3f64aa59,0xbee63375,0x3f43e200,0xbf24d225,0x3f187fc0,0xbf4d9f02,0x3ec9b953,0xbf6b4b0c,0x3e2f10a2,0xbf7c3b28,0xbd7b2b74,0xbf7f84ab,
0x3f800000,0x0,0x3f7853f8,0xbe78cfcc,0x3f61c598,0xbef15aea,0x3f3daef9,0xbf2beb4a,0x3f0e39da,0xbf54db31,0x3eac7cd4,0xbf710908,0x3dc8bd36,0xbf7ec46d,0xbe164083,0xbf7d3aac,
0x3f800000,0x0,0x3f778bc5,0xbe827dc0,0x3f5ebe05,0xbefc5d27,0x3f373a23,0xbf32c8c9,0x3f039c3d,0xbf5b941a,0x3e8e9a22,0xbf75dec6,0x3cc90ab0,0xbf7fec43,0xbe6c9a7f,0xbf791298,
0x3f800000,0x0,0x3f76ba07,0xbe888e93,0x3f5b941a,0xbf039c3d,0x3f3085bb,0xbf396842,0x3ef15aea,0xbf61c598,0x3e605c13,0xbf79c79d,0xbd48fb30,0xbf7fb10f,0xbea09ae5,0xbf731447,
0x3f800000,0x0,0x3f75dec6,0xbe8e9a22,0x3f584853,0xbf08f59b,0x3f299415,0xbf3fc767,0x3edae880,0xbf676bd8,0x3e22abb6,0xbf7cbfc9,0xbdfab273,0xbf7e1324,0xbec9b953,0xbf6b4b0c,
0x3f800000,0x0,0x3f7ec46d,0xbdc8bd36,0x3f7b14be,0xbe47c5c2,0x3f74fa0b,0xbe94a031,0x3f6c835e,0xbec3ef15,0x3f61c598,0xbef15aea,0x3f54db31,0xbf0e39da,0x3f45e403,0xbf226799,
0x3f800000,0x0,0x3f6b4b0c,0xbec9b953,0x3f3085bb,0xbf396842,0x3eb263ef,0xbf6ff573,0xbd48fb30,0xbf7fb10f,0xbee0924f,0xbf660f88,0xbf41d870,0xbf273656,0xbf740bdd,0xbe9aa086,
0x3f800000,0x0,0x3f6a09a7,0xbecf7bca,0x3f2beb4a,0xbf3daef9,0x3ea09ae5,0xbf731447,0xbdc8bd36,0xbf7ec46d,0xbefc5d27,0xbf5ebe05,0xbf4d9f02,0xbf187fc0,0xbf79c79d,0xbe605c13,
0x3f800000,0x0,0x3f68bf3c,0xbed53641,0x3f273656,0xbf41d870,0x3e8e9a22,0xbf75dec6,0xbe164083,0xbf7d3aac,0xbf0b9a6b,0xbf5695e5,0xbf584853,0xbf08f59b,0xbf7dabcc,0xbe09cf86,
0x3f800000,0x0,0x3f676bd8,0xbedae880,0x3f226799,0xbf45e403,0x3e78cfcc,0xbf7853f8,0xbe47c5c2,0xbf7b14be,0xbf187fc0,0xbf4d9f02,0xbf61c598,0xbef15aea,0xbf7fb10f,0xbd48fb30,
0x3f800000,0x0,0x3f660f88,0xbee0924f,0x3f1d7fd1,0xbf49d112,0x3e541501,0xbf7a7302,0xbe78cfcc,0xbf7853f8,0xbf24d225,0xbf43e200,0xbf6a09a7,0xbecf7bca,0xbf7fd397,0x3d16c32c,
0x3f800000,0x0,0x3f64aa59,0xbee63375,0x3f187fc0,0xbf4d9f02,0x3e2f10a2,0xbf7c3b28,0xbe94a031,0xbf74fa0b,0xbf3085bb,0xbf396842,0xbf710908,0xbeac7cd4,0xbf7e1324,0x3dfab273,
0x3f800000,0x0,0x3f633c5a,0xbeebcbbb,0x3f13682a,0xbf514d3d,0x3e09cf86,0xbf7dabcc,0xbeac7cd4,0xbf710908,0xbf3b8f3b,0xbf2e3bde,0xbf76ba07,0xbe888e93,0xbf7a7302,0x3e541501,
0x3f800000,0x0,0x3f74fa0b,0xbe94a031,0x3f54db31,0xbf0e39da,0x3f226799,0xbf45e403,0x3ec3ef15,0xbf6c835e,0x3dc8bd36,0xbf7ec46d,0xbe47c5c2,0xbf7b14be,0xbef15aea,0xbf61c598,
0x3f800000,0x0,0x3f531849,0xbf10d3cd,0x3eb8442a,0xbf6ed89e,0xbe6c9a7f,0xbf791298,0xbf3daef9,0xbf2beb4a,0xbf7dabcc,0xbe09cf86,0xbf64aa59,0x3ee63375,0xbef6e0cb,0x3f604621,
0x3f800000,0x0,0x3f514d3d,0xbf13682a,0x3eac7cd4,0xbf710908,0xbe888e93,0xbf76ba07,0xbf45e403,0xbf226799,0xbf7f4e6d,0xbd96a905,0xbf5b941a,0x3f039c3d,0xbecf7bca,0x3f6a09a7,
0x3f800000,0x0,0x3f4f7a1f,0xbf15f6d9,0x3ea09ae5,0xbf731447,0xbe9aa086,0xbf740bdd,0xbf4d9f02,0xbf187fc0,0xbf7ffb11,0xbc490e90,0xbf514d3d,0x3f13682a,0xbea68f12,0x3f721352,
0x3f800000,0x0,0x3f4d9f02,0xbf187fc0,0x3e94a031,0xbf74fa0b,0xbeac7cd4,0xbf710908,0xbf54db31,0xbf0e39da,0xbf7fb10f,0x3d48fb30,0xbf45e403,0x3f226799,0xbe78cfcc,0x3f7853f8,
0x3f800000,0x0,0x3f4bbbf8,0xbf1b02c6,0x3e888e93,0xbf76ba07,0xbebe1d4a,0xbf6db293,0xbf5b941a,0xbf039c3d,0xbf7e70b0,0x3de1bc2e,0xbf396842,0x3f3085bb,0xbe22abb6,0x3f7cbfc9,
0x3f800000,0x0,0x3f49d112,0xbf1d7fd1,0x3e78cfcc,0xbf7853f8,0xbecf7bca,0xbf6a09a7,0xbf61c598,0xbef15aea,0xbf7c3b28,0x3e2f10a2,0xbf2beb4a,0x3f3daef9,0xbd96a905,0x3f7f4e6d,
0x3f800000,0x0,0x3f47de65,0xbf1ff6cb,0x3e605c13,0xbf79c79d,0xbee0924f,0xbf660f88,0xbf676bd8,0xbedae880,0xbf791298,0x3e6c9a7f,0xbf1d7fd1,0x3f49d112,0x3c490e90,0x3f7ffb11,
0x3f800000,0x0,0x3f800000,0x0,0x3f800000,0x0,0x3f800000,0x0,0x40000000,0x0,0x3f800000,0x0,0x3f800000,0x0,0x3f800000,0x0,
0x3f800000,0x0,0x3f7ffb11,0xbc490e90,0x3f7fec43,0xbcc90ab0,0x3f7fd397,0xbd16c32c,0x3fffb10f,0xbdc8fb30,0x3f7f84ab,0xbd7b2b74,0x3f7f4e6d,0xbd96a905,0x3f7f0e58,0xbdafb680,
0x3f800000,0x0,0x3f7fec43,0xbcc90ab0,0x3f7fb10f,0xbd48fb30,0x3f7f4e6d,0xbd96a905,0x3ffec46d,0xbe48bd36,0x3f7e1324,0xbdfab273,0x3f7d3aac,0xbe164083,0x3f7c3b28,0xbe2f10a2,
0x3f800000,0x0,0x3f7fd397,0xbd16c32c,0x3f7f4e6d,0xbd96a905,0x3f7e70b0,0xbde1bc2e,0x3ffd3aac,0xbe964083,0x3f7baccd,0xbe3b6ecf,0x3f79c79d,0xbe605c13,0x3f778bc5,0xbe827dc0,
0x3f800000,0x0,0x3f7fb10f,0xbd48fb30,0x3f7ec46d,0xbdc8bd36,0x3f7d3aac,0xbe164083,0x3ffb14be,0xbec7c5c2,0x3f7853f8,0xbe78cfcc,0x3f74fa0b,0xbe94a031,0x3f710908,0xbeac7cd4,
0x3f800000,0x0,0x3f7f84ab,0xbd7b2b74,0x3f7e1324,0xbdfab273,0x3f7baccd,0xbe3b6ecf,0x3ff853f8,0xbef8cfcc,0x3f740bdd,0xbe9aa086,0x3f6ed89e,0xbeb8442a,0x3f68bf3c,0xbed53641,
0x3f800000,0x0,0x3f7f4e6d,0xbd96a905,0x3f7d3aac,0xbe164083,0x3f79c79d,0xbe605c13,0x3ff4fa0b,0xbf14a031,0x3f6ed89e,0xbeb8442a,0x3f676bd8,0xbedae880,0x3f5ebe05,0xbefc5d27,
0x3f800000,0x0,0x3f7f0e58,0xbdafb680,0x3f7c3b28,0xbe2f10a2,0x3f778bc5,0xbe827dc0,0x3ff10908,0xbf2c7cd4,0x3f68bf3c,0xbed53641,0x3f5ebe05,0xbefc5d27,0x3f531849,0xbf10d3cd,
0x3f800000,0x0,0x3f7ec46d,0xbdc8bd36,0x3f7b14be,0xbe47c5c2,0x3f74fa0b,0xbe94a031,0x3fec835e,0xbf43ef15,0x3f61c598,0xbef15aea,0x3f54db31,0xbf0e39da,0x3f45e403,0xbf226799,
0x3f800000,0x0,0x3f7e70b0,0xbde1bc2e,0x3f79c79d,0xbe605c13,0x3f721352,0xbea68f12,0x3fe76bd8,0xbf5ae880,0x3f59f26a,0xbf064b82,0x3f49d112,0xbf1d7fd1,0x3f373a23,0xbf32c8c9,
0x3f800000,0x0,0x3f7e1324,0xbdfab273,0x3f7853f8,0xbe78cfcc,0x3f6ed89e,0xbeb8442a,0x3fe1c598,0xbf715aea,0x3f514d3d,0xbf13682a,0x3f3daef9,0xbf2beb4a,0x3f273656,0xbf41d870,
0x3f800000,0x0,0x3f7dabcc,0xbe09cf86,0x3f76ba07,0xbe888e93,0x3f6b4b0c,0xbec9b953,0x3fdb941a,0xbf839c3d,0x3f47de65,0xbf1ff6cb,0x3f3085bb,0xbf396842,0x3f15f6d9,0xbf4f7a1f,
0x3f800000,0x0,0x3f7d3aac,0xbe164083,0x3f74fa0b,0xbe94a031,0x3f676bd8,0xbedae880,0x3fd4db31,0xbf8e39da,0x3f3daef9,0xbf2beb4a,0x3f226799,0xbf45e403,0x3f039c3d,0xbf5b941a,
0x3f800000,0x0,0x3f7cbfc9,0xbe22abb6,0x3f731447,0xbea09ae5,0x3f633c5a,0xbeebcbbb,0x3fcd9f02,0xbf987fc0,0x3f32c8c9,0xbf373a23,0x3f13682a,0xbf514d3d,0x3ee0924f,0xbf660f88,
0x3f800000,0x0,0x3f7c3b28,0xbe2f10a2,0x3f710908,0xbeac7cd4,0x3f5ebe05,0xbefc5d27,0x3fc5e403,0xbfa26799,0x3f273656,0xbf41d870,0x3f039c3d,0xbf5b941a,0x3eb8442a,0xbf6ed89e,
0x3f800000,0x0,0x3f7baccd,0xbe3b6ecf,0x3f6ed89e,0xbeb8442a,0x3f59f26a,0xbf064b82,0x3fbdaef9,0xbfabeb4a,0x3f1b02c6,0xbf4bbbf8,0x3ee63375,0xbf64aa59,0x3e8e9a22,0xbf75dec6,
0x3f800000,0x0,0x3f7b14be,0xbe47c5c2,0x3f6c835e,0xbec3ef15,0x3f54db31,0xbf0e39da,0x3fb504f3,0xbfb504f3,0x3f0e39da,0xbf54db31,0x3ec3ef15,0xbf6c835e,0x3e47c5c2,0xbf7b14be,
0x3f800000,0x0,0x3f7a7302,0xbe541501,0x3f6a09a7,0xbecf7bca,0x3f4f7a1f,0xbf15f6d9,0x3fabeb4a,0xbfbdaef9,0x3f00e7e4,0xbf5d2d53,0x3ea09ae5,0xbf731447,0x3de1bc2e,0xbf7e70b0,
0x3f800000,0x0,0x3f79c79d,0xbe605c13,0x3f676bd8,0xbedae880,0x3f49d112,0xbf1d7fd1,0x3fa26799,0xbfc5e403,0x3ee63375,0xbf64aa59,0x3e78cfcc,0xbf7853f8,0x3cc90ab0,0xbf7fec43,
0x3f800000,0x0,0x3f791298,0xbe6c9a7f,0x3f64aa59,0xbee63375,0x3f43e200,0xbf24d225,0x3f987fc0,0xbfcd9f02,0x3ec9b953,0xbf6b4b0c,0x3e2f10a2,0xbf7c3b28,0xbd7b2b74,0xbf7f84ab,
0x3f800000,0x0,0x3f7853f8,0xbe78cfcc,0x3f61c598,0xbef15aea,0x3f3daef9,0xbf2beb4a,0x3f8e39da,0xbfd4db31,0x3eac7cd4,0xbf710908,0x3dc8bd36,0xbf7ec46d,0xbe164083,0xbf7d3aac,
0x3f800000,0x0,0x3f778bc5,0xbe827dc0,0x3f5ebe05,0xbefc5d27,0x3f373a23,0xbf32c8c9,0x3f839c3d,0xbfdb941a,0x3e8e9a22,0xbf75dec6,0x3cc90ab0,0xbf7fec43,0xbe6c9a7f,0xbf791298,
0x3f800000,0x0,0x3f76ba07,0xbe888e93,0x3f5b941a,0xbf039c3d,0x3f3085bb,0xbf396842,0x3f715aea,0xbfe1c598,0x3e605c13,0xbf79c79d,0xbd48fb30,0xbf7fb10f,0xbea09ae5,0xbf731447,
0x3f800000,0x0,0x3f75dec6,0xbe8e9a22,0x3f584853,0xbf08f59b,0x3f299415,0xbf3fc767,0x3f5ae880,0xbfe76bd8,0x3e22abb6,0xbf7cbfc9,0xbdfab273,0xbf7e1324,0xbec9b953,0xbf6b4b0c,
0x3f800000,0x0,0x3f74fa0b,0xbe94a031,0x3f54db31,0xbf0e39da,0x3f226799,0xbf45e403,0x3f43ef15,0xbfec835e,0x3dc8bd36,0xbf7ec46d,0xbe47c5c2,0xbf7b14be,0xbef15aea,0xbf61c598,
0x3f800000,0x0,0x3f740bdd,0xbe9aa086,0x3f514d3d,0xbf13682a,0x3f1b02c6,0xbf4bbbf8,0x3f2c7cd4,0xbff10908,0x3d16c32c,0xbf7fd397,0xbe888e93,0xbf76ba07,0xbf0b9a6b,0xbf5695e5,
0x3f800000,0x0,0x3f731447,0xbea09ae5,0x3f4d9f02,0xbf187fc0,0x3f13682a,0xbf514d3d,0x3f14a031,0xbff4fa0b,0xbcc90ab0,0xbf7fec43,0xbeac7cd4,0xbf710908,0xbf1d7fd1,0xbf49d112,
0x3f800000,0x0,0x3f721352,0xbea68f12,0x3f49d112,0xbf1d7fd1,0x3f0b9a6b,0xbf5695e5,0x3ef8cfcc,0xbff853f8,0xbdafb680,0xbf7f0e58,0xbecf7bca,0xbf6a09a7,0xbf2e3bde,0xbf3b8f3b,
0x3f800000,0x0,0x3f710908,0xbeac7cd4,0x3f45e403,0xbf226799,0x3f039c3d,0xbf5b941a,0x3ec7c5c2,0xbffb14be,0xbe164083,0xbf7d3aac,0xbef15aea,0xbf61c598,0xbf3daef9,0xbf2beb4a,
0x3f800000,0x0,0x3f6ff573,0xbeb263ef,0x3f41d870,0xbf273656,0x3ef6e0cb,0xbf604621,0x3e964083,0xbffd3aac,0xbe541501,0xbf7a7302,0xbf08f59b,0xbf584853,0xbf4bbbf8,0xbf1b02c6,
0x3f800000,0x0,0x3f6ed89e,0xbeb8442a,0x3f3daef9,0xbf2beb4a,0x3ee63375,0xbf64aa59,0x3e48bd36,0xbffec46d,0xbe888e93,0xbf76ba07,0xbf187fc0,0xbf4d9f02,0xbf584853,0xbf08f59b,
0x3f800000,0x0,0x3f6db293,0xbebe1d4a,0x3f396842,0xbf3085bb,0x3ed53641,0xbf68bf3c,0x3dc8fb30,0xbfffb10f,0xbea68f12,0xbf721352,0xbf273656,0xbf41d870,0xbf633c5a,0xbeebcbbb,
0x3f800000,0x0,0x3f7fffb1,0xbb490fc6,0x3f7ffec4,0xbbc90f88,0x3f7ffd39,0xbc16cb58,0x3ffffb11,0xbcc90e90,0x3f7ff84a,0xbc7b514b,0x3f7ff4e6,0xbc96c9b6,0x3f7ff0e3,0xbcafea69,
0x3f800000,0x0,0x3f7ff84a,0xbc7b514b,0x3f7fe129,0xbcfb49ba,0x3f7fba9e,0xbd3c6dd5,0x3fff84ab,0xbdfb2b74,0x3f7f3f54,0xbd9cecf9,0x3f7eea9d,0xbdbc3ac3,0x3f7e868b,0xbddb7d37,
0x3f800000,0x0,0x3f7fe705,0xbce22a7a,0x3f7f9c18,0xbd621469,0x3f7f1f49,0xbda973ba,0x3ffe70b0,0xbe61bc2e,0x3f7d906e,0xbe0cec4a,0x3f7c7eb0,0xbe28defc,0x3f7b3bab,0xbe44b0b9,
0x3f800000,0x0,0x3f7fcbe2,0xbd2351cb,0x3f7f2f9d,0xbda3308c,0x3f7e2b72,0xbdf475c0,0x3ffcbfc9,0xbea2abb6,0x3f7aed37,0xbe4ada4f,0x3f78b47b,0xbe72b651,0x3f76167a,0xbe8d17c0,
0x3f800000,0x0,0x3f7fa6e3,0xbd55880e,0x3f7e9bc9,0xbdd53db9,0x3f7cdf6c,0xbe1f917b,0x3ffa7302,0xbed41501,0x3f77583a,0xbe840270,0x3f73913f,0xbe9d9e78,0x3f6f20b0,0xbeb6ccc3,
0x3f800000,0x0,0x3f7f7808,0xbd83db0a,0x3f7de0b1,0xbe039502,0x3f7b3bab,0xbe44b0b9,0x3ff78bc5,0xbf027dc0,0x3f72d4eb,0xbea21887,0x3f6d1c1d,0xbec1071e,0x3f666771,0xbedf28a9,
0x3f800000,0x0,0x3f7f3f54,0xbd9cecf9,0x3f7cfe73,0xbe1c76de,0x3f7940c0,0xbe698bba,0x3ff40bdd,0xbf1aa086,0x3f6d67a1,0xbebf926f,0x3f655e0b,0xbee363fa,0x3f5bfb34,0xbf02ef9f,
0x3f800000,0x0,0x3f7efcc9,0xbdb5f8da,0x3f7bf531,0xbe354098,0x3f76ef5b,0xbe870ada,0x3feff573,0xbf3263ef,0x3f671599,0xbedc53c1,0x3f5c61c7,0xbf0242b1,0x3f4fefa8,0xbf1553b7,
0x3f800000,0x0,0x3f7eb069,0xbdcefdb7,0x3f7ac516,0xbe4dee60,0x3f74484b,0xbe9920fe,0x3feb4b0c,0xbf49b953,0x3f5fe4e9,0xbef840c8,0x3f5233c6,0xbf121eb0,0x3f425b89,0xbf269de3,
0x3f800000,0x0,0x3f7e5a38,0xbde7fa9a,0x3f796e4e,0xbe667c66,0x3f714c7a,0xbeab0201,0x3fe60f88,0xbf60924f,0x3f57dc7f,0xbf099f4e,0x3f46e22a,0xbf212ff9,0x3f33587a,0xbf36ad7f,
0x3f800000,0x0,0x3f7dfa38,0xbe007745,0x3f77f110,0xbe7ee6e1,0x3f6dfcf2,0xbebca7af,0x3fe04621,0xbf76e0cb,0x3f4f0417,0xbf16999f,0x3f3a7ca4,0xbf2f61a5,0x3f2302d3,0xbf456439,
0x3f800000,0x0,0x3f7d906e,0xbe0cec4a,0x3f764d97,0xbe8b9507,0x3f6a5ad9,0xbece0bea,0x3fd9f26a,0xbf864b82,0x3f456439,0xbf2302d3,0x3f2d1469,0xbf3ca003,0x3f11796b,0xbf52a649,
0x3f800000,0x0,0x3f7d1cdd,0xbe195be0,0x3f748422,0xbe97a117,0x3f666771,0xbedf28a9,0x3fd31849,0xbf90d3cd,0x3f3b0629,0xbf2ecef7,0x3f1ebc12,0xbf48d8b3,0x3efdbabb,0xbf5e5aa6,
0x3f800000,0x0,0x3f7c9f8a,0xbe25c58c,0x3f7294f8,0xbea395c5,0x3f62241a,0xbeeff7fb,0x3fcbbbf8,0xbf9b02c6,0x3f2ff3e6,0xbf39f2ac,0x3f0f8784,0xbf53fac3,0x3ed6a399,0xbf686b39,
0x3f800000,0x0,0x3f7c187a,0xbe3228d4,0x3f708066,0xbeaf713a,0x3f5d924d,0xbf003a06,0x3fc3e200,0xbfa4d225,0x3f24381a,0xbf446337,0x3eff17b2,0xbf5df6be,0x3eadf73c,0xbf70c501,
0x3f800000,0x0,0x3f7b87b2,0xbe3e853e,0x3f6e46be,0xbebb31a0,0x3f58b3a1,0xbf084b92,0x3fbb8f3b,0xbfae3bde,0x3f17de12,0xbf4e1689,0x3eddbe79,0xbf66becc,0x3e840270,0xbf77583a,
0x3f800000,0x0,0x3f7aed37,0xbe4ada4f,0x3f6be858,0xbec6d529,0x3f5389c7,0xbf102dd5,0x3fb2c8c9,0xbfb73a23,0x3f0af1b7,0xbf570348,0x3ebb31a0,0xbf6e46be,0x3e3228d4,0xbf7c187a,
0x3f800000,0x0,0x3f7a4910,0xbe57278f,0x3f696591,0xbed25a09,0x3f4e1689,0xbf17de12,0x3fa99415,0xbfbfc767,0x3efafef7,0xbf5f20db,0x3e97a117,0xbf748422,0x3db5f8da,0xbf7efcc9,
0x3f800000,0x0,0x3f799b43,0xbe636c83,0x3f66becc,0xbeddbe79,0x3f485bca,0xbf1f599f,0x3f9ff6cb,0xbfc7de65,0x3edf28a9,0xbf666771,0x3e667c66,0xbf796e4e,0x3b490fc6,0xbf7fffb1,
0x3f800000,0x0,0x3f78e3d6,0xbe6fa8b2,0x3f63f473,0xbee900b7,0x3f425b89,0xbf269de3,0x3f95f6d9,0xbfcf7a1f,0x3ec27b55,0xbf6cd007,0x3e1c76de,0xbf7cfe73,0xbda973ba,0xbf7f1f49,
0x3f800000,0x0,0x3f7822d1,0xbe7bdba4,0x3f6106f2,0xbef41f07,0x3f3c17d9,0xbf2da859,0x3f8b9a6b,0xbfd695e5,0x3ea5129f,0xbf725470,0x3da3308c,0xbf7f2f9d,0xbe2bf804,0xbf7c5d3a,
0x3f800000,0x0,0x3f77583a,0xbe840270,0x3f5df6be,0xbeff17b2,0x3f3592e7,0xbf34768f,0x3f80e7e4,0xbfdd2d53,0x3e870ada,0xbf76ef5b,0x3bc90f88,0xbf7ffec4,0xbe80f8c0,0xbf77beb7,
0x3f800000,0x0,0x3f76841b,0xbe8a11f7,0x3f5ac450,0xbf04f484,0x3f2ecef7,0xbf3b0629,0x3f6bcbbb,0xbfe33c5a,0x3e5101f1,0xbf7a9c59,0xbd8a200a,0xbf7f6ac7,0xbeab0201,0xbf714c7a,
0x3f800000,0x0,0x3f75a67b,0xbe901c2c,0x3f577026,0xbf0a48ad,0x3f27ce61,0xbf4154e1,0x3f553641,0xbfe8bf3c,0x3e1324ca,0xbf7d57de,0xbe1008b7,0xbf7d7474,0xbed3c867,0xbf6912ae,
0x3f800000,0x0,0x3f74bf62,0xbe9620d2,0x3f53fac3,0xbf0f8784,0x3f209393,0xbf476085,0x3f3e1d4a,0xbfedb293,0x3da973ba,0xbf7f1f49,0xbe5a3997,0xbf7a1e84,0xbefafef7,0xbf5f20db,
0x3f800000,0x0,0x3f73ced9,0xbe9c1faf,0x3f5064af,0xbf14b039,0x3f19210f,0xbf4d26fd,0x3f268f12,0xbff21352,0x3cafea69,0xbf7ff0e3,0xbe919ddd,0xbf756d97,0xbf102dd5,0xbf5389c7,
0x3f800000,0x0,0x3f72d4eb,0xbea21887,0x3f4cae79,0xbf19c200,0x3f11796b,0xbf52a649,0x3f0e9a22,0xbff5dec6,0xbd2351cb,0xbf7fcbe2,0xbeb554ec,0xbf6f6830,0xbf21cbfb,0xbf466354,
0x3f800000,0x0,0x3f71d19f,0xbea80b1f,0x3f48d8b3,0xbf1ebc12,0x3f099f4e,0xbf57dc7f,0x3eec9a7f,0xbff91298,0xbdcefdb7,0xbf7eb069,0xbed8106b,0xbf6816a8,0xbf3238aa,0xbf37c655,
0x3f800000,0x0,0x3f70c501,0xbeadf73c,0x3f44e3f5,0xbf239da9,0x3f019573,0xbf5cc7d1,0x3ebb6ecf,0xbffbaccd,0xbe25c58c,0xbf7c9f8a,0xbef9a02d,0xbf5f8327,0xbf4154e1,0xbf27ce61,
0x3f800000,0x0,0x3f6faf1b,0xbeb3dca5,0x3f40d0da,0xbf286605,0x3ef2bd43,0xbf61668a,0x3e89cf86,0xbffdabcc,0xbe636c83,0xbf799b43,0xbf0cead0,0xbf55b993,0xbf4f0417,0xbf16999f,
0x3f800000,0x0,0x3f6e8ff8,0xbeb9bb1e,0x3f3ca003,0xbf2d1469,0x3ee1fb6a,0xbf65b710,0x3e2fb680,0xbfff0e58,0xbe901c2c,0xbf75a67b,0xbf1c420c,0xbf4ac77f,0xbf5b2c79,0xbf044889,
0x3f800000,0x0,0x3f6d67a1,0xbebf926f,0x3f385216,0xbf31a81d,0x3ed0eb2a,0xbf69b7e4,0x3d96c32c,0xbfffd397,0xbeadf73c,0xbf70c501,0xbf2ac082,0xbf3ebc1b,0xbf65b710,0xbee1fb6a,
0x3f800000,0x0,0x3f7ffec4,0xbbc90f88,0x3f7ffb11,0xbc490e90,0x3f7ff4e6,0xbc96c9b6,0x3fffec43,0xbd490ab0,0x3f7fe129,0xbcfb49ba,0x3f7fd397,0xbd16c32c,0x3f7fc38f,0xbd2fe007,
0x3f800000,0x0,0x3f7ff4e6,0xbc96c9b6,0x3f7fd397,0xbd16c32c,0x3f7f9c18,0xbd621469,0x3fff4e6d,0xbe16a905,0x3f7eea9d,0xbdbc3ac3,0x3f7e70b0,0xbde1bc2e,0x3f7de0b1,0xbe039502,
0x3f800000,0x0,0x3f7fe129,0xbcfb49ba,0x3f7f84ab,0xbd7b2b74,0x3f7eea9d,0xbdbc3ac3,0x3ffe1324,0xbe7ab273,0x3f7cfe73,0xbe1c76de,0x3f7baccd,0xbe3b6ecf,0x3f7a1e84,0xbe5a3997,
0x3f800000,0x0,0x3f7fc38f,0xbd2fe007,0x3f7f0e58,0xbdafb680,0x3f7de0b1,0xbe039502,0x3ffc3b28,0xbeaf10a2,0x3f7a1e84,0xbe5a3997,0x3f778bc5,0xbe827dc0,0x3f748422,0xbe97a117,
0x3f800000,0x0,0x3f7f9c18,0xbd621469,0x3f7e70b0,0xbde1bc2e,0x3f7c7eb0,0xbe28defc,0x3ff9c79d,0xbee05c13,0x3f764d97,0xbe8b9507,0x3f721352,0xbea68f12,0x3f6d1c1d,0xbec1071e,
0x3f800000,0x0,0x3f7f6ac7,0xbd8a200a,0x3f7dabcc,0xbe09cf86,0x3f7ac516,0xbe4dee60,0x3ff6ba07,0xbf088e93,0x3f718f57,0xbea986c4,0x3f6b4b0c,0xbec9b953,0x3f63f473,0xbee900b7,
0x3f800000,0x0,0x3f7f2f9d,0xbda3308c,0x3f7cbfc9,0xbe22abb6,0x3f78b47b,0xbe72b651,0x3ff31447,0xbf209ae5,0x3f6be858,0xbec6d529,0x3f633c5a,0xbeebcbbb,0x3f591e6a,0xbf07a136,
0x3f800000,0x0,0x3f7eea9d,0xbdbc3ac3,0x3f7baccd,0xbe3b6ecf,0x3f764d97,0xbe8b9507,0x3feed89e,0xbf38442a,0x3f655e0b,0xbee363fa,0x3f59f26a,0xbf064b82,0x3f4cae79,0xbf19c200,
0x3f800000,0x0,0x3f7e9bc9,0xbdd53db9,0x3f7a7302,0xbe541501,0x3f73913f,0xbe9d9e78,0x3fea09a7,0xbf4f7bca,0x3f5df6be,0xbeff17b2,0x3f4f7a1f,0xbf15f6d9,0x3f3ebc1b,0xbf2ac082,
0x3f800000,0x0,0x3f7e4323,0xbdee3876,0x3f791298,0xbe6c9a7f,0x3f708066,0xbeaf713a,0x3fe4aa59,0xbf663375,0x3f55b993,0xbf0cead0,0x3f43e200,0xbf24d225,0x3f2f61a5,0xbf3a7ca4,
0x3f800000,0x0,0x3f7de0b1,0xbe039502,0x3f778bc5,0xbe827dc0,0x3f6d1c1d,0xbec1071e,0x3fdebe05,0xbf7c5d27,0x3f4cae79,0xbf19c200,0x3f373a23,0xbf32c8c9,0x3f1ebc12,0xbf48d8b3,
0x3f800000,0x0,0x3f7d7474,0xbe1008b7,0x3f75dec6,0xbe8e9a22,0x3f696591,0xbed25a09,0x3fd84853,0xbf88f59b,0x3f42de29,0xbf26050a,0x3f299415,0xbf3fc767,0x3f0cead0,0xbf55b993,
0x3f800000,0x0,0x3f7cfe73,0xbe1c76de,0x3f740bdd,0xbe9aa086,0x3f655e0b,0xbee363fa,0x3fd14d3d,0xbf93682a,0x3f385216,0xbf31a81d,0x3f1b02c6,0xbf4bbbf8,0x3ef41f07,0xbf6106f2,
0x3f800000,0x0,0x3f7c7eb0,0xbe28defc,0x3f721352,0xbea68f12,0x3f6106f2,0xbef41f07,0x3fc9d112,0xbf9d7fd1,0x3f2d1469,0xbf3ca003,0x3f0b9a6b,0xbf5695e5,0x3ecc9b8b,0xbf6aab7b,
0x3f800000,0x0,0x3f7bf531,0xbe354098,0x3f6ff573,0xbeb263ef,0x3f5c61c7,0xbf0242b1,0x3fc1d870,0xbfa73656,0x3f212ff9,0xbf46e22a,0x3ef6e0cb,0xbf604621,0x3ea395c5,0xbf7294f8,
0x3f800000,0x0,0x3f7b61fc,0xbe419b37,0x3f6db293,0xbebe1d4a,0x3f577026,0xbf0a48ad,0x3fb96842,0xbfb085bb,0x3f14b039,0xbf5064af,0x3ed53641,0xbf68bf3c,0x3e72b651,0xbf78b47b,
0x3f800000,0x0,0x3f7ac516,0xbe4dee60,0x3f6b4b0c,0xbec9b953,0x3f5233c6,0xbf121eb0,0x3fb085bb,0xbfb96842,0x3f07a136,0xbf591e6a,0x3eb263ef,0xbf6ff573,0x3e1c76de,0xbf7cfe73,
0x3f800000,0x0,0x3f7a1e84,0xbe5a3997,0x3f68bf3c,0xbed53641,0x3f4cae79,0xbf19c200,0x3fa73656,0xbfc1d870,0x3ef41f07,0xbf6106f2,0x3e8e9a22,0xbf75dec6,0x3d8a200a,0xbf7f6ac7,
0x3f800000,0x0,0x3f796e4e,0xbe667c66,0x3f660f88,0xbee0924f,0x3f46e22a,0xbf212ff9,0x3f9d7fd1,0xbfc9d112,0x3ed8106b,0xbf6816a8,0x3e541501,0xbf7a7302,0xbc96c9b6,0xbf7ff4e6,
0x3f800000,0x0,0x3f78b47b,0xbe72b651,0x3f633c5a,0xbeebcbbb,0x3f40d0da,0xbf286605,0x3f93682a,0xbfd14d3d,0x3ebb31a0,0xbf6e46be,0x3e09cf86,0xbf7dabcc,0xbdd53db9,0xbf7e9bc9,
0x3f800000,0x0,0x3f77f110,0xbe7ee6e1,0x3f604621,0xbef6e0cb,0x3f3a7ca4,0xbf2f61a5,0x3f88f59b,0xbfd84853,0x3e9d9e78,0xbf73913f,0x3d7b2b74,0xbf7f84ab,0xbe419b37,0xbf7b61fc,
0x3f800000,0x0,0x3f772417,0xbe8586ce,0x3f5d2d53,0xbf00e7e4,0x3f33e7bc,0xbf36206c,0x3f7c5d27,0xbfdebe05,0x3e7ee6e1,0xbf77f110,0xbc490e90,0xbf7ffb11,0xbe8b9507,0xbf764d97,
0x3f800000,0x0,0x3f764d97,0xbe8b9507,0x3f59f26a,0xbf064b82,0x3f2d1469,0xbf3ca003,0x3f663375,0xbfe4aa59,0x3e419b37,0xbf7b61fc,0xbdafb680,0xbf7f0e58,0xbeb554ec,0xbf6f6830,
0x3f800000,0x0,0x3f756d97,0xbe919ddd,0x3f5695e5,0xbf0b9a6b,0x3f26050a,0xbf42de29,0x3f4f7bca,0xbfea09a7,0x3e039502,0xbf7de0b1,0xbe22abb6,0xbf7cbfc9,0xbeddbe79,0xbf66becc,
0x3f800000,0x0,0x3f748422,0xbe97a117,0x3f531849,0xbf10d3cd,0x3f1ebc12,0xbf48d8b3,0x3f38442a,0xbfeed89e,0x3d8a200a,0xbf7f6ac7,0xbe6c9a7f,0xbf791298,0xbf0242b1,0xbf5c61c7,
0x3f800000,0x0,0x3f73913f,0xbe9d9e78,0x3f4f7a1f,0xbf15f6d9,0x3f173c07,0xbf4e8d90,0x3f209ae5,0xbff31447,0x3bc90f88,0xbf7ffec4,0xbe9aa086,0xbf740bdd,0xbf14b039,0xbf5064af,
0x3f800000,0x0,0x3f7294f8,0xbea395c5,0x3f4bbbf8,0xbf1b02c6,0x3f0f8784,0xbf53fac3,0x3f088e93,0xbff6ba07,0xbd621469,0xbf7f9c18,0xbebe1d4a,0xbf6db293,0xbf26050a,0xbf42de29,
0x3f800000,0x0,0x3f718f57,0xbea986c4,0x3f47de65,0xbf1ff6cb,0x3f07a136,0xbf591e6a,0x3ee05c13,0xbff9c79d,0xbdee3876,0xbf7e4323,0xbee0924f,0xbf660f88,0xbf36206c,0xbf33e7bc,
0x3f800000,0x0,0x3f708066,0xbeaf713a,0x3f43e200,0xbf24d225,0x3eff17b2,0xbf5df6be,0x3eaf10a2,0xbffc3b28,0xbe354098,0xbf7bf531,0xbf00e7e4,0xbf5d2d53,0xbf44e3f5,0xbf239da9,
0x3f800000,0x0,0x3f6f6830,0xbeb554ec,0x3f3fc767,0xbf299415,0x3eee9479,0xbf628210,0x3e7ab273,0xbffe1324,0xbe72b651,0xbf78b47b,0xbf10d3cd,0xbf531849,0xbf5233c6,0xbf121eb0,
0x3f800000,0x0,0x3f6e46be,0xbebb31a0,0x3f3b8f3b,0xbf2e3bde,0x3eddbe79,0xbf66becc,0x3e16a905,0xbfff4e6d,0xbe97a117,0xbf748422,0xbf1ff6cb,0xbf47de65,0xbf5df6be,0xbeff17b2,
0x3f800000,0x0,0x3f6d1c1d,0xbec1071e,0x3f373a23,0xbf32c8c9,0x3ecc9b8b,0xbf6aab7b,0x3d490ab0,0xbfffec43,0xbeb554ec,0xbf6f6830,0xbf2e3bde,0xbf3b8f3b,0xbf6816a8,0xbed8106b,
0x3f800000,0x0,0x3f7ffd39,0xbc16cb58,0x3f7ff4e6,0xbc96c9b6,0x3f7fe705,0xbce22a7a,0x3fffd397,0xbd96c32c,0x3f7fba9e,0xbd3c6dd5,0x3f7f9c18,0xbd621469,0x3f7f7808,0xbd83db0a,
0x3f800000,0x0,0x3f7ff0e3,0xbcafea69,0x3f7fc38f,0xbd2fe007,0x3f7f7808,0xbd83db0a,0x3fff0e58,0xbe2fb680,0x3f7e868b,0xbddb7d37,0x3f7de0b1,0xbe039502,0x3f7d1cdd,0xbe195be0,
0x3f800000,0x0,0x3f7fdaaf,0xbd0a342f,0x3f7f6ac7,0xbd8a200a,0x3f7eb069,0xbdcefdb7,0x3ffdabcc,0xbe89cf86,0x3f7c5d3a,0xbe2bf804,0x3f7ac516,0xbe4dee60,0x3f78e3d6,0xbe6fa8b2,
0x3f800000,0x0,0x3f7fba9e,0xbd3c6dd5,0x3f7eea9d,0xbdbc3ac3,0x3f7d906e,0xbe0cec4a,0x3ffbaccd,0xbebb6ecf,0x3f7940c0,0xbe698bba,0x3f764d97,0xbe8b9507,0x3f72d4eb,0xbea21887,
0x3f800000,0x0,0x3f7f90b1,0xbd6ea038,0x3f7e4323,0xbdee3876,0x3f7c187a,0xbe3228d4,0x3ff91298,0xbeec9a7f,0x3f75341d,0xbe931f35,0x3f708066,0xbeaf713a,0x3f6afb8c,0xbecb2aae,
0x3f800000,0x0,0x3f7f5ce9,0xbd9064b4,0x3f7d7474,0xbe1008b7,0x3f7a4910,0xbe57278f,0x3ff5dec6,0xbf0e9a22,0x3f703b37,0xbeb0eacb,0x3f696591,0xbed25a09,0x3f61668a,0xbef2bd43,
0x3f800000,0x0,0x3f7f1f49,0xbda973ba,0x3f7c7eb0,0xbe28defc,0x3f7822d1,0xbe7bdba4,0x3ff21352,0xbf268f12,0x3f6a5ad9,0xbece0bea,0x3f6106f2,0xbef41f07,0x3f5627fe,0xbf0c42c9,
0x3f800000,0x0,0x3f7ed7d4,0xbdc27c39,0x3f7b61fc,0xbe419b37,0x3f75a67b,0xbe901c2c,0x3fedb293,0xbf3e1d4a,0x3f6398ac,0xbeea6681,0x3f577026,0xbf0a48ad,0x3f495521,0xbf1e1e22,
0x3f800000,0x0,0x3f7e868b,0xbddb7d37,0x3f7a1e84,0xbe5a3997,0x3f72d4eb,0xbea21887,0x3fe8bf3c,0xbf553641,0x3f5bfb34,0xbf02ef9f,0x3f4cae79,0xbf19c200,0x3f3b0629,0xbf2ecef7,
0x3f800000,0x0,0x3f7e2b72,0xbdf475c0,0x3f78b47b,0xbe72b651,0x3f6faf1b,0xbeb3dca5,0x3fe33c5a,0xbf6bcbbb,0x3f5389c7,0xbf102dd5,0x3f40d0da,0xbf286605,0x3f2b561b,0xbf3e35c5,
0x3f800000,0x0,0x3f7dc68c,0xbe06b26e,0x3f772417,0xbe8586ce,0x3f6c3624,0xbec5625c,0x3fdd2d53,0xbf80e7e4,0x3f4a4c87,0xbf1ce11f,0x3f33e7bc,0xbf36206c,0x3f1a6293,0xbf4c3578,
0x3f800000,0x0,0x3f7d57de,0xbe1324ca,0x3f756d97,0xbe919ddd,0x3f686b39,0xbed6a399,0x3fd695e5,0xbf8b9a6b,0x3f404c5c,0xbf28fd41,0x3f26050a,0xbf42de29,0x3f084b92,0xbf58b3a1,
0x3f800000,0x0,0x3f7cdf6c,0xbe1f917b,0x3f73913f,0xbe9d9e78,0x3f644fac,0xbee79a5d,0x3fcf7a1f,0xbf95f6d9,0x3f3592e7,0xbf34768f,0x3f173c07,0xbf4e8d90,0x3eea6681,0xbf6398ac,
0x3f800000,0x0,0x3f7c5d3a,0xbe2bf804,0x3f718f57,0xbea986c4,0x3f5fe4e9,0xbef840c8,0x3fc7de65,0xbf9ff6cb,0x3f2a2a80,0xbf3f41fc,0x3f07a136,0xbf591e6a,0x3ec27b55,0xbf6cd007,
0x3f800000,0x0,0x3f7bd14d,0xbe3857ec,0x3f6f6830,0xbeb554ec,0x3f5b2c79,0xbf044889,0x3fbfc767,0xbfa99415,0x3f1e1e22,0xbf495521,0x3eee9479,0xbf628210,0x3e9920fe,0xbf74484b,
0x3f800000,0x0,0x3f7b3bab,0xbe44b0b9,0x3f6d1c1d,0xbec1071e,0x3f5627fe,0xbf0c42c9,0x3fb73a23,0xbfb2c8c9,0x3f11796b,0xbf52a649,0x3ecc9b8b,0xbf6aab7b,0x3e5d4b1a,0xbf79f35e,
0x3f800000,0x0,0x3f7a9c59,0xbe5101f1,0x3f6aab7b,0xbecc9b8b,0x3f50d937,0xbf140c5f,0x3fae3bde,0xbfbb8f3b,0x3f044889,0xbf5b2c79,0x3ea986c4,0xbf718f57,0x3e06b26e,0xbf7dc68c,
0x3f800000,0x0,0x3f79f35e,0xbe5d4b1a,0x3f6816a8,0xbed8106b,0x3f4b41fa,0xbf1ba299,0x3fa4d225,0xbfc3e200,0x3eed3063,0xbf62df7b,0x3e8586ce,0xbf772417,0x3d3c6dd5,0xbf7fba9e,
0x3f800000,0x0,0x3f7940c0,0xbe698bba,0x3f655e0b,0xbee363fa,0x3f456439,0xbf2302d3,0x3f9b02c6,0xbfcbbbf8,0x3ed0eb2a,0xbf69b7e4,0x3e419b37,0xbf7b61fc,0xbd2351cb,0xbf7fcbe2,
0x3f800000,0x0,0x3f788486,0xbe75c35a,0x3f628210,0xbeee9479,0x3f3f41fc,0xbf2a2a80,0x3f90d3cd,0xbfd31849,0x3eb3dca5,0xbf6faf1b,0x3dee3876,0xbf7e4323,0xbe007745,0xbf7dfa38,
0x3f800000,0x0,0x3f77beb7,0xbe80f8c0,0x3f5f8327,0xbef9a02d,0x3f38dd65,0xbf311722,0x3f864b82,0xbfd9f26a,0x3e9620d2,0xbf74bf62,0x3d2fe007,0xbf7fc38f,0xbe57278f,0xbf7a4910,
0x3f800000,0x0,0x3f76ef5b,0xbe870ada,0x3f5c61c7,0xbf0242b1,0x3f3238aa,0xbf37c655,0x3f76e0cb,0xbfe04621,0x3e6fa8b2,0xbf78e3d6,0xbcfb49ba,0xbf7fe129,0xbe9620d2,0xbf74bf62,
0x3f800000,0x0,0x3f76167a,0xbe8d17c0,0x3f591e6a,0xbf07a136,0x3f2b561b,0xbf3e35c5,0x3f60924f,0xbfe60f88,0x3e3228d4,0xbf7c187a,0xbdd53db9,0xbf7e9bc9,0xbebf926f,0xbf6d67a1,
0x3f800000,0x0,0x3f75341d,0xbe931f35,0x3f55b993,0xbf0cead0,0x3f24381a,0xbf446337,0x3f49b953,0xbfeb4b0c,0x3de7fa9a,0xbf7e5a38,0xbe354098,0xbf7bf531,0xbee79a5d,0xbf644fac,
0x3f800000,0x0,0x3f74484b,0xbe9920fe,0x3f5233c6,0xbf121eb0,0x3f1ce11f,0xbf4a4c87,0x3f3263ef,0xbfeff573,0x3d55880e,0xbf7fa6e3,0xbe7ee6e1,0xbf77f110,0xbf06f686,0xbf5988ad,
0x3f800000,0x0,0x3f73530e,0xbe9f1cdf,0x3f4e8d90,0xbf173c07,0x3f1553b7,0xbf4fefa8,0x3f1aa086,0xbff40bdd,0xbc16cb58,0xbf7ffd39,0xbea395c5,0xbf7294f8,0xbf19210f,0xbf4d26fd,
0x3f800000,0x0,0x3f725470,0xbea5129f,0x3f4ac77f,0xbf1c420c,0x3f0d9281,0xbf554aa4,0x3f027dc0,0xbff78bc5,0xbd9064b4,0xbf7f5ce9,0xbec6d529,0xbf6be858,0xbf2a2a80,0xbf3f41fc,
0x3f800000,0x0,0x3f714c7a,0xbeab0201,0x3f46e22a,0xbf212ff9,0x3f05a02c,0xbf5a5ba0,0x3ed41501,0xbffa7302,0xbe06b26e,0xbf7dc68c,0xbee900b7,0xbf63f473,0xbf39f2ac,0xbf2ff3e6,
0x3f800000,0x0,0x3f703b37,0xbeb0eacb,0x3f42de29,0xbf26050a,0x3efafef7,0xbf5f20db,0x3ea2abb6,0xbffcbfc9,0xbe44b0b9,0xbf7b3bab,0xbf04f484,0xbf5ac450,0xbf485bca,0xbf1f599f,
0x3f800000,0x0,0x3f6f20b0,0xbeb6ccc3,0x3f3ebc1b,0xbf2ac082,0x3eea6681,0xbf6398ac,0x3e61bc2e,0xbffe70b0,0xbe80f8c0,0xbf77beb7,0xbf14b039,0xbf5064af,0xbf554aa4,0xbf0d9281,
0x3f800000,0x0,0x3f6dfcf2,0xbebca7af,0x3f3a7ca4,0xbf2f61a5,0x3ed97cb9,0xbf67c187,0x3dfb2b74,0xbfff84ab,0xbe9f1cdf,0xbf73530e,0xbf239da9,0xbf44e3f5,0xbf60a6cf,0xbef58035,
0x3f800000,0x0,0x3f6cd007,0xbec27b55,0x3f36206c,0xbf33e7bc,0x3ec8477c,0xbf6b99fb,0x3cc90e90,0xbffffb11,0xbebca7af,0xbf6dfcf2,0xbf31a81d,0xbf385216,0xbf6a5ad9,0xbece0bea,
0x3f800000,0x0,0x0,0x0,0x0,0x0,0x0,0x0,0x0,0x0,0x0,0x0,0x0,0x0,0x0,0x0,
0x0,0x0,0x0,0x0,0x0,0x0,0x0,0x0,0x0,0x0,0x0,0x0,0x0,0x0,0x0,0x0,
0x0,0x0,0x3e000000,0xbf20dff7,0x3ed0c429,0x0,0x3e000000,0x3e61f78b,0x3e0a8bd4,0x0,0x3e000000,0x3d5413cd,0x3d5df9ad,0x0,0x3e000000,0x3cf043ab,
0x0,0x0,0x3e000000,0x3ccbafaf,0xbd5df9ad,0x0,0x3e000000,0x3cf043ab,0xbe0a8bd4,0x0,0x3e000000,0x3d5413cd,0xbed0c429,0x0,0x3e000000,0x3e61f78b,
0x0,0x0,0x0,0x0,0x3f000000,0x0,0x0,0x3f000000,0x0,0x0,0x0,0x0,0x0,0x0,0x0,0x0,
0x0,0x0,0x0,0x0,0x0,0x0,0x0,0x0,0x0,0x0,0x0,0x0,0x3f000000,0x0,0x0,0xbf000000,
0x0,0x0,0x3e000000,0xbe3f90c7,0xbe8b7e3f,0x0,0x3e000000,0xbeb641af,0x3ea73d75,0x0,0x3e000000,0x3e9a827a,0x3da61ad1,0x0,0x3e000000,0x3dd906bd,
0x0,0x0,0x3e000000,0x3dab0dc1,0xbda61ad1,0x0,0x3e000000,0x3dd906bd,0xbea73d75,0x0,0x3e000000,0x3e9a827a,0x3e8b7e3f,0x0,0x3e000000,0xbeb641af,
0x0,0x0,0x0,0x0,0x0,0x0,0x0,0x0,0x3f000000,0x0,0x0,0x3f000000,0x0,0x0,0x0,0x0,
0x0,0x0,0x0,0x0,0x0,0x0,0x0,0x0,0x3f000000,0x0,0x0,0xbf000000,0x0,0x0,0x0,0x0,
0x0,0x0,0x3e000000,0xbdab0dc1,0xbda61ad1,0x0,0x3e000000,0xbdd906bd,0xbea73d75,0x0,0x3e000000,0xbe9a827a,0x3e8b7e3f,0x0,0x3e000000,0x3eb641af,
0x0,0x0,0x3e000000,0x3e3f90c7,0xbe8b7e3f,0x0,0x3e000000,0x3eb641af,0x3ea73d75,0x0,0x3e000000,0xbe9a827a,0x3da61ad1,0x0,0x3e000000,0xbdd906bd,
0x0,0x0,0x0,0x0,0x0,0x0,0x0,0x0,0x0,0x0,0x0,0x0,0x3f000000,0x0,0x0,0x3f000000,
0x0,0x0,0x0,0x0,0x3f000000,0x0,0x0,0xbf000000,0x0,0x0,0x0,0x0,0x0,0x0,0x0,0x0,
0x0,0x0,0x3e000000,0xbccbafaf,0xbd5df9ad,0x0,0x3e000000,0xbcf043ab,0xbe0a8bd4,0x0,0x3e000000,0xbd5413cd,0xbed0c429,0x0,0x3e000000,0xbe61f78b,
0x0,0x0,0x3e000000,0x3f20dff7,0x3ed0c429,0x0,0x3e000000,0xbe61f78b,0x3e0a8bd4,0x0,0x3e000000,0xbd5413cd,0x3d5df9ad,0x0,0x3e000000,0xbcf043ab,
};

struct Params {
    const __nv_bfloat16 *wr, *wi, *lre, *lim, *ldt, *dsk;
    float* out;
};

struct cf { float x, y; };
#define YIELD() asm volatile("pmevent 1;")
#define YS 14
#define YIELD_S1() do { if (YS & 1) YIELD(); } while (0)
#define YIELD_S2() do { if (YS & 2) YIELD(); } while (0)
#define YIELD_S3() do { if (YS & 4) YIELD(); } while (0)
__device__ __forceinline__ uint32_t smem_u32(const void* p) { return (uint32_t)__cvta_generic_to_shared(p); }
__device__ __forceinline__ void mbar_init(uint32_t a, uint32_t c) { asm volatile("mbarrier.init.shared::cta.b64 [%0], %1;" ::"r"(a), "r"(c) : "memory"); }
__device__ __forceinline__ void mbar_expect_tx(uint32_t a, uint32_t b) { asm volatile("mbarrier.arrive.expect_tx.shared::cta.b64 _, [%0], %1;" ::"r"(a), "r"(b) : "memory"); }
__device__ __forceinline__ void mbar_arrive(uint32_t a) { asm volatile("mbarrier.arrive.shared::cta.b64 _, [%0];" ::"r"(a) : "memory"); }
__device__ __forceinline__ void warp_arrive(uint32_t a) {
    __syncwarp();
    asm volatile("{.reg .pred p; elect.sync _|p, 0xffffffff; @p mbarrier.arrive.shared::cta.b64 _, [%0];}" ::"r"(a) : "memory");
}
__device__ __forceinline__ uint32_t mbar_try(uint32_t a, uint32_t ph) {
    uint32_t ok;
    asm volatile("{.reg .pred p; mbarrier.try_wait.parity.shared::cta.b64 p, [%1], %2; selp.u32 %0, 1, 0, p;}" : "=r"(ok) : "r"(a), "r"(ph) : "memory");
    return ok;
}
__device__ __forceinline__ void mbar_wait(uint32_t a, uint32_t ph) {
    uint32_t ok, n = 0;
    do { ok = mbar_try(a, ph); } while (!ok && ++n < SPIN_LIMIT);
}
__device__ __forceinline__ void mbar_wait_fast(uint32_t a, uint32_t ph) { if (!mbar_try(a, ph)) mbar_wait(a, ph); }
__device__ __forceinline__ unsigned ld_rlx(const unsigned* p) { unsigned v; asm volatile("ld.relaxed.gpu.global.u32 %0, [%1];" : "=r"(v) : "l"(p) : "memory"); return v; }
__device__ __forceinline__ void wait_cnt(const unsigned* p, unsigned target) {
    unsigned n = 0;
    while ((int)(ld_rlx(p) - target) < 0 && ++n < SPIN_LIMIT) __nanosleep(20);
}
__device__ __forceinline__ void red_hint(unsigned* p) { asm volatile("red.relaxed.gpu.global.add.u32 [%0], 1;" ::"l"(p) : "memory"); }
__device__ __forceinline__ void fence_async() { asm volatile("fence.proxy.async.global;" ::: "memory"); }
__device__ __forceinline__ void fence_async_sm() { asm volatile("fence.proxy.async.shared::cta;" ::: "memory"); }
#define bar_sync(id, n) asm volatile("bar.sync %0, %1;" ::"n"(id), "n"(n) : "memory")
#define bar_arrive(id, n) asm volatile("bar.arrive %0, %1;" ::"n"(id), "n"(n) : "memory")
__device__ __forceinline__ bool elect_one() {
    uint32_t r;
    asm volatile("{.reg .pred p; elect.sync _|p, 0xffffffff; selp.u32 %0, 1, 0, p;}" : "=r"(r));
    return r != 0;
}

__device__ __forceinline__ void tma2d(uint32_t dst, const CUtensorMap* m, int c0, int c1, uint32_t bar) {
    asm volatile("cp.async.bulk.tensor.2d.shared::cluster.global.mbarrier::complete_tx::bytes [%0], [%1, {%3,%4}], [%2];" ::"r"(dst), "l"(m), "r"(bar), "r"(c0), "r"(c1) : "memory");
}
__device__ __forceinline__ void tma3d(uint32_t dst, const CUtensorMap* m, int c0, int c1, int c2, uint32_t bar) {
    asm volatile("cp.async.bulk.tensor.3d.shared::cluster.global.mbarrier::complete_tx::bytes [%0], [%1, {%3,%4,%5}], [%2];" ::"r"(dst), "l"(m), "r"(bar), "r"(c0), "r"(c1), "r"(c2) : "memory");
}
__device__ __forceinline__ void tma2d_mc(uint32_t dst, const CUtensorMap* m, int c0, int c1, uint32_t bar) {
    asm volatile("cp.async.bulk.tensor.2d.shared::cluster.global.mbarrier::complete_tx::bytes.multicast::cluster [%0], [%1, {%3,%4}], [%2], %5;" ::"r"(dst), "l"(m), "r"(bar), "r"(c0), "r"(c1), "h"((uint16_t)3) : "memory");
}
__device__ __forceinline__ void tma4d_mc(uint32_t dst, const CUtensorMap* m, int c0, int c1, int c2, int c3, uint32_t bar) {
    asm volatile("cp.async.bulk.tensor.4d.shared::cluster.global.mbarrier::complete_tx::bytes.multicast::cluster [%0], [%1, {%3,%4,%5,%6}], [%2], %7;" ::"r"(dst), "l"(m), "r"(bar), "r"(c0), "r"(c1), "r"(c2), "r"(c3), "h"((uint16_t)3) : "memory");
}
__device__ __forceinline__ void tma4d(uint32_t dst, const CUtensorMap* m, int c0, int c1, int c2, int c3, uint32_t bar) {
    asm volatile("cp.async.bulk.tensor.4d.shared::cluster.global.mbarrier::complete_tx::bytes [%0], [%1, {%3,%4,%5,%6}], [%2];" ::"r"(dst), "l"(m), "r"(bar), "r"(c0), "r"(c1), "r"(c2), "r"(c3) : "memory");
}
__device__ __forceinline__ void tma2d_st(const CUtensorMap* m, int c0, int c1, uint32_t src) {
    asm volatile("cp.async.bulk.tensor.2d.global.shared::cta.bulk_group [%0, {%2,%3}], [%1];" ::"l"(m), "r"(src), "r"(c0), "r"(c1) : "memory");
}
__device__ __forceinline__ void tma3d_st(const CUtensorMap* m, int c0, int c1, int c2, uint32_t src) {
    asm volatile("cp.async.bulk.tensor.3d.global.shared::cta.bulk_group [%0, {%2,%3,%4}], [%1];" ::"l"(m), "r"(src), "r"(c0), "r"(c1), "r"(c2) : "memory");
}
__device__ __forceinline__ void tma5d(uint32_t dst, const CUtensorMap* m, int c0, int c1, int c2, int c3, int c4, uint32_t bar) {
    asm volatile("cp.async.bulk.tensor.5d.shared::cluster.global.mbarrier::complete_tx::bytes [%0], [%1, {%3,%4,%5,%6,%7}], [%2];" ::"r"(dst), "l"(m), "r"(bar), "r"(c0), "r"(c1), "r"(c2), "r"(c3), "r"(c4) : "memory");
}
__device__ __forceinline__ void tma5d_mc(uint32_t dst, const CUtensorMap* m, int c0, int c1, int c2, int c3, int c4, uint32_t bar) {
    asm volatile("cp.async.bulk.tensor.5d.shared::cluster.global.mbarrier::complete_tx::bytes.multicast::cluster [%0], [%1, {%3,%4,%5,%6,%7}], [%2], %8;" ::"r"(dst), "l"(m), "r"(bar), "r"(c0), "r"(c1), "r"(c2), "r"(c3), "r"(c4), "h"((uint16_t)3) : "memory");
}
__device__ __forceinline__ void bulk_pf(const void* src, uint32_t n) { asm volatile("cp.async.bulk.prefetch.L2.global [%0], %1;" ::"l"(src), "r"(n) : "memory"); }
__device__ __forceinline__ void tma4d_pf(const CUtensorMap* m, int c0, int c1, int c2, int c3) {
    asm volatile("cp.async.bulk.prefetch.tensor.4d.L2.global [%0, {%1,%2,%3,%4}];" ::"l"(m), "r"(c0), "r"(c1), "r"(c2), "r"(c3) : "memory");
}
__device__ __forceinline__ void tma5d_pf(const CUtensorMap* m, int c0, int c1, int c2, int c3, int c4) {
    asm volatile("cp.async.bulk.prefetch.tensor.5d.L2.global [%0, {%1,%2,%3,%4,%5}];" ::"l"(m), "r"(c0), "r"(c1), "r"(c2), "r"(c3), "r"(c4) : "memory");
}
__device__ __forceinline__ void bulk_ld(uint32_t dst, const void* src, uint32_t n, uint32_t bar) {
    asm volatile("cp.async.bulk.shared::cluster.global.mbarrier::complete_tx::bytes [%0], [%1], %2, [%3];" ::"r"(dst), "l"(src), "r"(n), "r"(bar) : "memory");
}
__device__ __forceinline__ void bulk_st(void* dst, uint32_t src, uint32_t n) {
    asm volatile("cp.async.bulk.global.shared::cta.bulk_group [%0], [%1], %2;" ::"l"(dst), "r"(src), "r"(n) : "memory");
}
__device__ __forceinline__ void bulk_commit() { asm volatile("cp.async.bulk.commit_group;" ::: "memory"); }
__device__ __forceinline__ void bulk_wait_read() { asm volatile("cp.async.bulk.wait_group.read 0;" ::: "memory"); }
__device__ __forceinline__ void bulk_wait_all() { asm volatile("cp.async.bulk.wait_group 0;" ::: "memory"); }
__device__ __forceinline__ void stsm4(uint32_t a, uint32_t r0, uint32_t r1, uint32_t r2, uint32_t r3) {
    asm volatile("stmatrix.sync.aligned.m8n8.x4.shared.b16 [%0], {%1,%2,%3,%4};" ::"r"(a), "r"(r0), "r"(r1), "r"(r2), "r"(r3) : "memory");
}
__device__ __forceinline__ void sts128(uint32_t a, uint32_t r0, uint32_t r1, uint32_t r2, uint32_t r3) {
    asm volatile("st.shared.v4.b32 [%0], {%1,%2,%3,%4};" ::"r"(a), "r"(r0), "r"(r1), "r"(r2), "r"(r3) : "memory");
}
__device__ __forceinline__ void lds128f(uint32_t a, float& x, float& y, float& z, float& u) { asm volatile("ld.shared.v4.f32 {%0,%1,%2,%3}, [%4];" : "=f"(x), "=f"(y), "=f"(z), "=f"(u) : "r"(a) : "memory"); }
__device__ __forceinline__ cf lds_cf(uint32_t a) { cf v; asm volatile("ld.shared.v2.f32 {%0,%1}, [%2];" : "=f"(v.x), "=f"(v.y) : "r"(a) : "memory"); return v; }
__device__ __forceinline__ void stg128(const void* a, uint32_t r0, uint32_t r1, uint32_t r2, uint32_t r3) {
    asm volatile("st.global.v4.b32 [%0], {%1,%2,%3,%4};" ::"l"(a), "r"(r0), "r"(r1), "r"(r2), "r"(r3) : "memory");
}
__device__ __forceinline__ int fresh_lane() { int v; asm volatile("mov.u32 %0, %%laneid;" : "=r"(v)); return v; }
__device__ __forceinline__ uint32_t opaque32(uint32_t v) { asm volatile("" : "+r"(v)); return v; }
__device__ __forceinline__ const uint8_t* padd(const void* base, uint32_t off) {
    uint64_t r;
    asm("{.reg .u32 l, h; mov.b64 {l, h}, %1; add.cc.u32 l, l, %2; addc.u32 h, h, 0; mov.b64 %0, {l, h};}" : "=l"(r) : "l"(base), "r"(off));
    return (const uint8_t*)r;
}
template <int N, int STRIDE> __device__ __forceinline__ void ldtab(uint32_t (&v)[4 * N], uint32_t off) {
    const uint8_t* a = padd(g_tab, off);
#pragma unroll
    for (int i = 0; i < N; i++)
        asm volatile("ld.global.nc.v4.b32 {%0,%1,%2,%3}, [%4];" : "=r"(v[4 * i]), "=r"(v[4 * i + 1]), "=r"(v[4 * i + 2]), "=r"(v[4 * i + 3]) : "l"(a + i * STRIDE));
}
template <int STRIDE> __device__ __forceinline__ void ldtab_cf(cf (&t)[8], uint32_t off) {
    uint32_t v[16];
    ldtab<4, STRIDE>(v, off);
#pragma unroll
    for (int i = 0; i < 8; i++) t[i] = {__uint_as_float(v[2 * i]), __uint_as_float(v[2 * i + 1])};
}
__device__ __forceinline__ uint32_t lds16(uint32_t a) { uint32_t v; asm volatile("ld.shared.u16 %0, [%1];" : "=r"(v) : "r"(a)); return v; }
__device__ __forceinline__ unsigned get_epoch(uint32_t bars) {
    mbar_wait(bars + B_EP, 0);
    unsigned e;
    asm volatile("ld.shared.u32 %0, [%1];" : "=r"(e) : "r"(bars + B_EPOCH) : "memory");
    return e;
}
__device__ __forceinline__ void sts64(uint32_t a, uint32_t x, uint32_t y) { asm volatile("st.shared.v2.b32 [%0], {%1,%2};" ::"r"(a), "r"(x), "r"(y) : "memory"); }
__device__ __forceinline__ uint32_t pk(float lo, float hi) { uint32_t r; asm("cvt.rn.bf16x2.f32 %0, %1, %2;" : "=r"(r) : "f"(hi), "f"(lo)); return r; }
__device__ __forceinline__ float bf2f(unsigned short v) { return __uint_as_float((uint32_t)v << 16); }

__device__ __forceinline__ uint64_t mkdesc(uint32_t addr, uint32_t lbo, uint32_t sbo, uint32_t swz) {
    return (uint64_t)((addr & 0x3FFFF) >> 4) | ((uint64_t)(lbo >> 4) << 16) | ((uint64_t)(sbo >> 4) << 32) | ((uint64_t)swz << 62);
}
__device__ __forceinline__ uint64_t opaque(uint64_t v) { asm volatile("" : "+l"(v)); return v; }
__device__ __forceinline__ void wg_fence() { asm volatile("wgmma.fence.sync.aligned;" ::: "memory"); }
__device__ __forceinline__ void wg_commit() { asm volatile("wgmma.commit_group.sync.aligned;" ::: "memory"); }
template <int N> __device__ __forceinline__ void wg_wait() { asm volatile("wgmma.wait_group.sync.aligned %0;" ::"n"(N) : "memory"); }
template <int N> __device__ __forceinline__ void pin(float (&d)[N]) {
#pragma unroll
    for (int i = 0; i < N; i++) asm volatile("" : "+f"(d[i])::"memory");
}
template <int N> __device__ __forceinline__ void pinu(uint32_t (&d)[N]) {
#pragma unroll
    for (int i = 0; i < N; i++) asm volatile("" : "+r"(d[i])::"memory");
}

#define R8(d, o) "+f"(d[o]), "+f"(d[o + 1]), "+f"(d[o + 2]), "+f"(d[o + 3]), "+f"(d[o + 4]), "+f"(d[o + 5]), "+f"(d[o + 6]), "+f"(d[o + 7])
#define L8 "%0,%1,%2,%3,%4,%5,%6,%7"
#define L32 L8 ",%8,%9,%10,%11,%12,%13,%14,%15,%16,%17,%18,%19,%20,%21,%22,%23,%24,%25,%26,%27,%28,%29,%30,%31"
#define L56 L32 ",%32,%33,%34,%35,%36,%37,%38,%39,%40,%41,%42,%43,%44,%45,%46,%47,%48,%49,%50,%51,%52,%53,%54,%55"
#define L64 L56 ",%56,%57,%58,%59,%60,%61,%62,%63"

template <int O, int TA, int TB, int N> __device__ __forceinline__ void mma128_ss(float (&d)[N], uint64_t da, uint64_t db, int sc) {
    asm volatile("{.reg .pred p; setp.ne.b32 p, %66, 0;\n"
                 "wgmma.mma_async.sync.aligned.m64n128k16.f32.bf16.bf16 {" L64 "}, %64, %65, p, 1, 1, %67, %68;}"
                 : R8(d, O), R8(d, O + 8), R8(d, O + 16), R8(d, O + 24), R8(d, O + 32), R8(d, O + 40), R8(d, O + 48), R8(d, O + 56)
                 : "l"(da), "l"(db), "r"(sc), "n"(TA), "n"(TB));
}
template <int O, int TB> __device__ __forceinline__ void mma128_rs(float (&d)[128], uint32_t a0, uint32_t a1, uint32_t a2, uint32_t a3, uint64_t db, int sc) {
    asm volatile("{.reg .pred p; setp.ne.b32 p, %69, 0;\n"
                 "wgmma.mma_async.sync.aligned.m64n128k16.f32.bf16.bf16 {" L64 "}, {%64,%65,%66,%67}, %68, p, 1, 1, %70;}"
                 : R8(d, O), R8(d, O + 8), R8(d, O + 16), R8(d, O + 24), R8(d, O + 32), R8(d, O + 40), R8(d, O + 48), R8(d, O + 56)
                 : "r"(a0), "r"(a1), "r"(a2), "r"(a3), "l"(db), "r"(sc), "n"(TB));
}
template <int TB> __device__ __forceinline__ void mma64_rs(float (&d)[32], uint32_t a0, uint32_t a1, uint32_t a2, uint32_t a3, uint64_t db, int sc) {
    asm volatile("{.reg .pred p; setp.ne.b32 p, %37, 0;\n"
                 "wgmma.mma_async.sync.aligned.m64n64k16.f32.bf16.bf16 {" L32 "}, {%32,%33,%34,%35}, %36, p, 1, 1, %38;}"
                 : R8(d, 0), R8(d, 8), R8(d, 16), R8(d, 24)
                 : "r"(a0), "r"(a1), "r"(a2), "r"(a3), "l"(db), "r"(sc), "n"(TB));
}
__device__ __forceinline__ void mma112_ss(float (&d)[64], uint64_t da, uint64_t db, int sc) {
    asm volatile("{.reg .pred p; setp.ne.b32 p, %58, 0;\n"
                 "wgmma.mma_async.sync.aligned.m64n112k16.f32.bf16.bf16 {" L56 "}, %56, %57, p, 1, 1, 0, 1;}"
                 : R8(d, 8), R8(d, 16), R8(d, 24), R8(d, 32), R8(d, 40), R8(d, 48), R8(d, 56)
                 : "l"(da), "l"(db), "r"(sc));
}
__device__ __forceinline__ void mma16_rs(float (&d)[64], uint32_t a0, uint32_t a1, uint32_t a2, uint32_t a3, uint64_t db, int sc) {
    asm volatile("{.reg .pred p; setp.ne.b32 p, %13, 0;\n"
                 "wgmma.mma_async.sync.aligned.m64n16k16.f32.bf16.bf16 {" L8 "}, {%8,%9,%10,%11}, %12, p, 1, 1, 1;}"
                 : R8(d, 0)
                 : "r"(a0), "r"(a1), "r"(a2), "r"(a3), "l"(db), "r"(sc));
}

__device__ __forceinline__ cf cmul(cf a, cf b) { return {fmaf(a.x, b.x, -a.y * b.y), fmaf(a.x, b.y, a.y * b.x)}; }
__device__ __forceinline__ cf cmulc(cf a, cf b) { return {fmaf(a.x, b.x, a.y * b.y), fmaf(a.y, b.x, -a.x * b.y)}; }
__device__ __forceinline__ cf cfma(cf a, cf b, cf c) { return {fmaf(a.x, b.x, fmaf(-a.y, b.y, c.x)), fmaf(a.x, b.y, fmaf(a.y, b.x, c.y))}; }
__device__ __forceinline__ cf csq(cf a) { return {fmaf(a.x, a.x, -a.y * a.y), (a.x * a.y) * 2.f}; }
__device__ __forceinline__ cf csel(int c, cf a, cf b) {
    cf r;
    asm("{.reg .pred p; setp.ne.s32 p, %2, 0; selp.f32 %0, %3, %5, p; selp.f32 %1, %4, %6, p;}" : "=f"(r.x), "=f"(r.y) : "r"(c), "f"(a.x), "f"(a.y), "f"(b.x), "f"(b.y));
    return r;
}
__device__ __forceinline__ cf cadd(cf a, cf b) { return {a.x + b.x, a.y + b.y}; }
__device__ __forceinline__ cf csub(cf a, cf b) { return {a.x - b.x, a.y - b.y}; }
__device__ __forceinline__ cf twice_minus(cf a, cf s) { return {fmaf(2.f, a.x, -s.x), fmaf(2.f, a.y, -s.y)}; }
__device__ __forceinline__ cf twid(int m, int M) {
    int r = ((m + M / 2) & (M - 1)) - M / 2;
    float s, c;
    __sincosf((float)r * (-6.283185307179586f / (float)M), &s, &c);
    return {c, s};
}
struct c2 { cf a, b; };
#define YP1 3
#define YP2 0
#define YP3 3
template <int Y> __device__ __forceinline__ void fin(c2& u) { if (Y & 1) asm volatile("pmevent 1;" : "+f"(u.a.x), "+f"(u.a.y), "+f"(u.b.x), "+f"(u.b.y)); }
template <int Y> __device__ __forceinline__ void fin(c2& u, c2& v) {
    if (Y & 2) asm volatile("pmevent 1;" : "+f"(u.a.x), "+f"(u.a.y), "+f"(u.b.x), "+f"(u.b.y), "+f"(v.a.x), "+f"(v.a.y), "+f"(v.b.x), "+f"(v.b.y));
}
__device__ __forceinline__ c2 mul2(c2 u, cf t) { return {cmul(u.a, t), cmul(u.b, t)}; }
__device__ __forceinline__ c2 mul2(c2 u, c2 t) { return {cmul(u.a, t.a), cmul(u.b, t.b)}; }
__device__ __forceinline__ c2 fma2(c2 u, cf t, c2 c) { return {cfma(u.a, t, c.a), cfma(u.b, t, c.b)}; }
__device__ __forceinline__ c2 fma2(c2 u, c2 t, c2 c) { return {cfma(u.a, t.a, c.a), cfma(u.b, t.b, c.b)}; }
__device__ __forceinline__ c2 twm2(c2 u, c2 s) { return {twice_minus(u.a, s.a), twice_minus(u.b, s.b)}; }
template <int Y> __device__ __forceinline__ void bfly(c2& u, c2& v) { const c2 t = u; u = {cadd(t.a, v.a), cadd(t.b, v.b)}; v = {csub(t.a, v.a), csub(t.b, v.b)}; fin<Y>(u, v); }
template <int Y> __device__ __forceinline__ void bfly_mi(c2& u, c2& v) {
    const c2 t = u, z = v;
    u = {{t.a.x + z.a.y, t.a.y - z.a.x}, {t.b.x + z.b.y, t.b.y - z.b.x}};
    v = {{t.a.x - z.a.y, t.a.y + z.a.x}, {t.b.x - z.b.y, t.b.y + z.b.x}};
    fin<Y>(u, v);
}
template <int Y> __device__ __forceinline__ void bfly_s(c2& u, c2& v) {
    const float s = 0.70710678118654752f;
    const c2 t = u, z = v;
    u = {{fmaf(s, z.a.x, t.a.x), fmaf(s, z.a.y, t.a.y)}, {fmaf(s, z.b.x, t.b.x), fmaf(s, z.b.y, t.b.y)}};
    v = {{fmaf(-s, z.a.x, t.a.x), fmaf(-s, z.a.y, t.a.y)}, {fmaf(-s, z.b.x, t.b.x), fmaf(-s, z.b.y, t.b.y)}};
    fin<Y>(u, v);
}
template <int Y, class T> __device__ __forceinline__ void bfly_tw(c2& u0, c2& v0, T t0, c2& u1, c2& v1, T t1) {
    v0 = fma2(v0, t0, u0); fin<Y>(v0);
    v1 = fma2(v1, t1, u1); fin<Y>(v1);
    const c2 a = twm2(u0, v0), b = twm2(u1, v1);
    u0 = v0; u1 = v1; v0 = a; v1 = b;
    fin<Y>(v0, v1);
}
template <bool TW, int Y> __device__ __forceinline__ void dft8(c2 (&v)[8], const cf (&tw)[8]) {
    if (TW) {
#pragma unroll
        for (int n = 1; n < 4; n++) { v[n] = mul2(v[n], tw[n]); fin<Y>(v[n]); }
        bfly_tw<Y>(v[0], v[4], tw[4], v[2], v[6], tw[6]);
        bfly_tw<Y>(v[1], v[5], tw[5], v[3], v[7], tw[7]);
    } else {
#pragma unroll
        for (int n = 0; n < 4; n++) bfly<Y>(v[n], v[n + 4]);
    }
    bfly<Y>(v[0], v[2]); bfly_mi<Y>(v[4], v[6]);
    bfly<Y>(v[1], v[3]); bfly_mi<Y>(v[5], v[7]);
    v[5] = {{v[5].a.x + v[5].a.y, v[5].a.y - v[5].a.x}, {v[5].b.x + v[5].b.y, v[5].b.y - v[5].b.x}};
    v[7] = {{v[7].a.y - v[7].a.x, -v[7].a.x - v[7].a.y}, {v[7].b.y - v[7].b.x, -v[7].b.x - v[7].b.y}};
    fin<Y>(v[5], v[7]);
    bfly<Y>(v[0], v[1]); bfly_s<Y>(v[4], v[5]); bfly_mi<Y>(v[2], v[3]); bfly_s<Y>(v[6], v[7]);
    const c2 t1 = v[1], t3 = v[3];
    v[1] = v[4]; v[4] = t1; v[3] = v[6]; v[6] = t3;
}

__device__ __forceinline__ void gather(uint64_t (&fv)[4], const uint8_t* a, int n) {
    asm volatile("{.reg .pred p0, p1, p2, p3;\n"
                 "setp.ge.s32 p0, %5, 0; setp.ge.s32 p1, %5, 4; setp.ge.s32 p2, %5, 8; setp.ge.s32 p3, %5, 12;\n"
                 "@p0 ld.relaxed.gpu.global.b64 %0, [%4]; @p1 ld.relaxed.gpu.global.b64 %1, [%4+-32768];\n"
                 "@p2 ld.relaxed.gpu.global.b64 %2, [%4+-65536]; @p3 ld.relaxed.gpu.global.b64 %3, [%4+-98304];}"
                 : "+l"(fv[0]), "+l"(fv[1]), "+l"(fv[2]), "+l"(fv[3]) : "l"(a), "r"(n) : "memory");
}
__device__ __forceinline__ cf as_cf(uint64_t v) { cf r; asm("mov.b64 {%0,%1}, %2;" : "=f"(r.x), "=f"(r.y) : "l"(v)); return r; }
template <int H> __device__ __forceinline__ void prescale(float (&u)[64], const float (&d)[128], cf gam) {
#pragma unroll
    for (int i = 0; i < 32; i += 2) {
        const int r = 2 * i + 2 * H;
        c2 v = mul2(c2{{d[r], -d[64 + r]}, {d[r + 1], -d[65 + r]}}, gam);
        if (YS & 2) asm volatile("pmevent 1;" : "+f"(v.a.x), "+f"(v.a.y), "+f"(v.b.x), "+f"(v.b.y));
        u[i] = v.a.x; u[32 + i] = v.a.y; u[i + 1] = v.b.x; u[33 + i] = v.b.y;
    }
}
__device__ __forceinline__ void scan2(const float (&u)[64], cf lam, cf st, const uint8_t* hptr, uint32_t hm, uint32_t hb, uint32_t& keep) {
    uint32_t hp[32];
#pragma unroll
    for (int jj = 0; jj < 4; jj++) {
        cf v[8];
#pragma unroll
        for (int i = 0; i < 8; i++) v[i] = st = cfma(lam, st, {u[8 * jj + i], u[32 + 8 * jj + i]});
        const int o = 8 * jj;
        hp[o] = pk(v[0].x, v[2].x); hp[o + 1] = pk(v[4].x, v[6].x); hp[o + 2] = pk(v[1].x, v[3].x); hp[o + 3] = pk(v[5].x, v[7].x);
        hp[o + 4] = pk(v[0].y, v[2].y); hp[o + 5] = pk(v[4].y, v[6].y); hp[o + 6] = pk(v[1].y, v[3].y); hp[o + 7] = pk(v[5].y, v[7].y);
        hp[o + jj] = (hp[o + jj] & hm) | hb;
        hp[o + 4 + jj] = (hp[o + 4 + jj] & hm) | hb;
        stg128(hptr + (jj >> 1) * 8192 + (jj & 1) * 512, hp[o], hp[o + 1], hp[o + 2], hp[o + 3]);
        stg128(hptr + 16384 + (jj >> 1) * 8192 + (jj & 1) * 512, hp[o + 4], hp[o + 5], hp[o + 6], hp[o + 7]);
        YIELD_S3();
        if (jj > 0) {
#pragma unroll
            for (int i = o - 8; i < o; i += 2) asm volatile("lop3.b32 %0, %0, %1, %2, 0x80;" : "+r"(keep) : "r"(hp[i]), "r"(hp[i + 1]));
        }
    }
}

__device__ __forceinline__ int pos_of(int n) { return (n & 24) + 4 * (n & 1) + ((n >> 1) & 3); }
__device__ __forceinline__ int unit_of(int role, int u, int& slot) {
    const int g = role & 7, w = (role >> 3) & 3, b = role >> 5;
    slot = role >= 128 ? g : (g ? 16 * g + w + 4 * b : 4 * w + b);
    return role >= 128 ? 32 * max(2 * g + u, 1) : (g ? g + 16 * w : ((w & 1) << 4) + ((w & 2) << 2)) + 64 * b + 256 * u;
}
template <int STRIDE> __device__ __forceinline__ bool tags_ok(uint32_t a, uint32_t ep) {
    uint32_t v[4], ok;
#pragma unroll
    for (int i = 0; i < 4; i++) {
        if (STRIDE || !i) asm volatile("ld.shared.u32 %0, [%1];" : "=r"(v[i]) : "r"(a + i * STRIDE) : "memory");
        else v[i] = v[0];
    }
    asm volatile("{.reg .pred p; .reg .b32 a, b; lop3.b32 a, %1, %2, %5, 0x7e; lop3.b32 b, %3, %4, %5, 0x7e; lop3.b32 a, a, b, 1, 0xa8;\n"
                 "setp.eq.u32 p, a, 0; vote.sync.all.pred p, p, -1; selp.u32 %0, 1, 0, p;}" : "=r"(ok) : "r"(v[0]), "r"(v[1]), "r"(v[2]), "r"(v[3]), "r"(ep));
    return ok;
}
__device__ __forceinline__ void load_w_rows(uint32_t dst, const CUtensorMap* mr, const CUtensorMap* mi, int kap, uint32_t bar) {
    mbar_expect_tx(bar, 16 * WPITCH);
#pragma unroll 1
    for (int i = 0; i < 2; i++, dst += 8 * WPITCH, kap = (512 - kap) & 511) {
        tma2d(dst, mr, (kap * 1026 >> 4) * 2, 0, bar);
        tma2d(dst + 4 * WPITCH, mi, (kap * 1026 >> 4) * 2, 0, bar);
    }
}
__device__ __forceinline__ void prefetch_w_rows(const CUtensorMap* mr, const CUtensorMap* mi, int kap) {
#pragma unroll 1
    for (int i = 0; i < 2; i++, kap = (512 - kap) & 511) {
        asm volatile("cp.async.bulk.prefetch.tensor.2d.L2.global [%0, {%1,%2}];" ::"l"(mr), "r"((kap * 1026 >> 4) * 2), "r"(0) : "memory");
        asm volatile("cp.async.bulk.prefetch.tensor.2d.L2.global [%0, {%1,%2}];" ::"l"(mi), "r"((kap * 1026 >> 4) * 2), "r"(0) : "memory");
    }
}
template <int K0, int K1> __device__ __forceinline__ void store_v(const uint32_t (&vo)[32], const uint8_t* vp, bool p) {
    if (p) {
#pragma unroll
        for (int k = K0; k < K1; k++)
            asm volatile("st.global.v2.b32 [%0], {%1,%2};" ::"l"(vp + (k >> 2) * (1 << 20) + ((k >> 1) & 1) * 8192 + (k & 1) * (4 * 32768)), "r"(vo[2 * k]), "r"(vo[2 * k + 1]) : "memory");
    }
}
__device__ __forceinline__ void hint_v(unsigned* cnt, int on) { asm volatile("{.reg .pred p; setp.ne.and.u32 p, %1, 0, p0; @p red.relaxed.gpu.global.add.u32 [%0], 1;}" ::"l"(cnt), "r"(on) : "memory"); }
#define SB0 1024
__device__ __forceinline__ uint64_t ring_desc(uint32_t sb, uint32_t off, uint32_t lbo, uint32_t swz) {
    uint64_t d;
    asm volatile("{.reg .b32 z; shr.u32 z, %1, 28; mov.b64 %0, {z, z}; add.u64 %0, %0, %2;}" : "=l"(d) : "r"(sb), "l"(mkdesc(SB0 + off, lbo, 1024, swz)));
    return d;
}
struct Ring {
    uint32_t full, rel;
    uint32_t n;
    bool sig;
};
__device__ __forceinline__ void ring_release(const Ring& r, uint32_t o) {
    if (r.sig) asm volatile("mbarrier.arrive.shared::cluster.b64 _, [%0];" ::"r"(r.rel + o) : "memory");
}
__device__ __forceinline__ void peek(uint32_t a, uint32_t ph) { asm volatile("mbarrier.test_wait.parity.shared::cta.b64 pk, [%0], %1;" ::"r"(a), "r"(ph) : "memory"); }
__device__ __forceinline__ void peek_wait(uint32_t a, uint32_t ph, uint32_t& n) {
    asm volatile("{@pk bra DONE;\n"
                 "LOOP: mbarrier.try_wait.parity.shared::cta.b64 pk, [%1], %2; add.u32 %0, %0, 1; setp.gt.or.u32 pk, %0, %3, pk; @!pk bra LOOP;\n"
                 "DONE: }" : "+r"(n) : "r"(a), "r"(ph), "n"(SPIN_LIMIT) : "memory");
}
#define SL(k) ((k) % NST)
#define PH(k) (((k) / NST) & 1)
#define HANDPOS 5
#define H64 "%64,%65,%66,%67,%68,%69,%70,%71,%72,%73,%74,%75,%76,%77,%78,%79,%80,%81,%82,%83,%84,%85,%86,%87,%88,%89,%90,%91,%92,%93,%94,%95," \
            "%96,%97,%98,%99,%100,%101,%102,%103,%104,%105,%106,%107,%108,%109,%110,%111,%112,%113,%114,%115,%116,%117,%118,%119,%120,%121,%122,%123,%124,%125,%126,%127"
#define WG_MMA "wgmma.mma_async.sync.aligned.m64n128k16.f32.bf16.bf16 "
#define DESC_B(S, j) "mov.b64 {t, hb}, %130; mov.b64 db, {%137 + 2048 * " #S " + 2 * " #j ", hb};\n"
#define MMA_LO(S, j, p) "add.u64 da, %129, 2048 * " #S " + %136 * " #j ";" DESC_B(S, j) WG_MMA "{" L64 "}, da, db, " #p ", 1, 1, %138, 0;\n"
#define MMA_HI(S, j, p) "add.u64 da, %129, 2048 * " #S " + 512 + %136 * " #j ";\n" WG_MMA "{" H64 "}, da, db, " #p ", 1, 1, %138, 0;\n"
#define X3(X)
#define X4(X)
#define X5(X) X
#define STEP(S, P, N, ph, pa, pr, X, Y) \
    "wgmma.fence.sync.aligned;\n" MMA_LO(S, 0, pa) MMA_HI(S, 0, pa) \
    "wgmma.commit_group.sync.aligned; wgmma.wait_group.sync.aligned 1; @" #pr " mbarrier.arrive.shared::cluster.b64 _, [%132 + 8 * " #P "];\n" MMA_LO(S, 1, 1) \
    "mbarrier.test_wait.parity.shared::cta.b64 pk, [%131 + 8 * " #N "], " #ph ";\n" X3(X) MMA_HI(S, 1, 1) X4(X) MMA_LO(S, 2, 1) X5(X) MMA_HI(S, 2, 1) MMA_LO(S, 3, 1) MMA_HI(S, 3, 1) \
    "wgmma.commit_group.sync.aligned;\n" P4A Y "@pk bra GO" #S ";\n" \
    "WAIT" #S ": mbarrier.try_wait.parity.shared::cta.b64 pk, [%131 + 8 * " #N "], " #ph "; add.u32 %128, %128, 1; setp.gt.or.u32 pk, %128, %139, pk; @!pk bra WAIT" #S ";\n" \
    "GO" #S ":\n" P4B
#define P4A
#define P4B
#define P4I
#define P4O
#define STEP_ARGS(TA) \
    : R8(d, 0), R8(d, 8), R8(d, 16), R8(d, 24), R8(d, 32), R8(d, 40), R8(d, 48), R8(d, 56), \
      R8(d, 64), R8(d, 72), R8(d, 80), R8(d, 88), R8(d, 96), R8(d, 104), R8(d, 112), R8(d, 120), "+r"(r.n) \
    : "l"(ha), "l"(hb), "r"(r.full), "r"(r.rel), "r"((uint32_t)r.sig), "r"(wg), \
      "n"(SB0 / 16 + (TA ? 32 << 16 : 1 << 16)), "n"(TA ? 128 : 2), "n"(SB0 / 16 + 1024 + (1 << 16)), "n"(TA), "n"(SPIN_LIMIT) P4O \
    : "memory"
#define STEP_REGS "{.reg .b32 k, t, ph, hb; .reg .b64 da, db; .reg .pred ps, pl, pa, pr;\n" P4I "setp.ne.u32 ps, %133, 0;\n"
#define FIRST_WAIT "FIRST: mbarrier.try_wait.parity.shared::cta.b64 pk, [t], ph; @pk bra START; add.u32 %128, %128, 1; setp.le.u32 pk, %128, %139; @pk bra FIRST; START:\n"
__device__ __forceinline__ void gemm1(float (&d)[128], Ring& r, uint64_t ha, uint64_t hb, int wg) {
    asm volatile(STEP_REGS "mul.lo.u32 k, %134, 15; mov.b32 ph, %134; setp.ne.u32 pl, k, 0; mad.lo.u32 t, %134, 8, %131;\n"
                 "pmevent 1; @pl bar.sync 1, 256;\n" FIRST_WAIT "@pl bra ONE;\n"
                 "LOOP: setp.ne.u32 pa, k, 0; and.pred pr, pa, ps; setp.eq.u32 pl, k, 15;\n"
                 STEP(0, 4, 1, ph, pa, pr, "@pl bar.arrive 1, 256;\n", "@pl bra END;\n")
                 "ONE: setp.ne.u32 pa, k, 15; and.pred pr, pa, ps; setp.eq.u32 pl, k, 30;\n"
                 STEP(1, 0, 2, ph, pa, pr, "@pl bar.arrive 2, 256;\n", "@pl bra END;\n")
                 STEP(2, 1, 3, ph, 1, ps, "", "") STEP(3, 2, 4, ph, 1, ps, "", "") "xor.b32 ph, ph, 1; add.u32 k, k, 5;\n" STEP(4, 3, 0, ph, 1, ps, "", "")
                 "bra LOOP;\n"
                 "END:\n" P4B "}" STEP_ARGS(0));
}
__device__ __forceinline__ void gemm2(float (&d)[128], Ring& r, uint64_t ha, uint64_t hb, int wg) {
    asm volatile(STEP_REGS "mov.b32 k, 0; mov.b32 ph, 0; add.u32 t, %131, 16;\n"
                 "pmevent 1; bar.sync 2, 256;\n" FIRST_WAIT
                 "LOOP: setp.ne.u32 pa, k, 0; and.pred pr, pa, ps; setp.eq.u32 pl, k, 5;\n"
                 STEP(2, 1, 3, ph, pa, pr, "", "") STEP(3, 2, 4, ph, 1, ps, "", "") "xor.b32 ph, ph, 1; add.u32 k, k, 1;\n" STEP(4, 3, 0, ph, 1, ps, "", "")
                 "@pl bra END;\n" STEP(0, 4, 1, ph, 1, ps, "", "") STEP(1, 0, 2, ph, 1, ps, "", "")
                 "bra LOOP;\n"
                 "END: }" STEP_ARGS(1));
}
template <int O, int K, int J> __device__ __forceinline__ void mma_h(float (&y)[128], uint64_t a, uint64_t b) { mma128_ss<O, 1, 0>(y, a + SL(K) * 2048 + O * 8 + 128 * J, b + SL(K) * 2048 + 2 * J, 1); }
template <int O, int K> __device__ __forceinline__ void half_step(float (&y)[128], uint64_t a, uint64_t b) { mma_h<O, K, 0>(y, a, b); mma_h<O, K, 1>(y, a, b); mma_h<O, K, 2>(y, a, b); mma_h<O, K, 3>(y, a, b); }
template <int R, int U> __device__ __forceinline__ void out_piece(float (&y)[128], const uint32_t (&dd)[16], uint32_t x0, uint32_t x1, float* op) {
    const int i = 64 * (R >> 1) + 8 * U + 2 * (R & 1);
    asm("mul.rn.bf16x2 %0, %0, %1;" : "+r"(x0) : "r"(dd[2 * U]));
    asm("mul.rn.bf16x2 %0, %0, %1;" : "+r"(x1) : "r"(dd[2 * U + 1]));
    asm volatile("st.global.v4.f32 [%0], {%1,%2,%3,%4};" ::"l"(op + (32 * (R & 1) + 16 * (R >> 1)) * 2048 + 16 * U),
                 "f"(y[i] + __uint_as_float(x0 << 16)), "f"(y[i + 1] + __uint_as_float(x0 & 0xffff0000u)),
                 "f"(y[i + 4] + __uint_as_float(x1 << 16)), "f"(y[i + 5] + __uint_as_float(x1 & 0xffff0000u)) : "memory");
}
template <int R, int U0> __device__ __forceinline__ void load_x4(uint32_t (&xx)[8], uint32_t xa) {
#pragma unroll
    for (int u = 0; u < 4; u++)
        asm volatile("ld.shared.v2.b32 {%0,%1}, [%2];" : "=r"(xx[2 * u]), "=r"(xx[2 * u + 1]) : "r"((xa ^ (u << 5)) + (3 - R) * 8192 + U0 * 1024) : "memory");
}
__device__ __forceinline__ Ring ring_at(uint32_t sb, int k) {
    Ring r;
    r.n = 0;
    r.full = sb + OFF_BAR + B_FULL;
    asm("mapa.shared::cluster.u32 %0, %1, %2;" : "=r"(r.rel) : "r"(sb + OFF_BAR + B_EMPTY), "r"((threadIdx.x >> 5) & 1));
    r.sig = __shfl_sync(~0u, threadIdx.x & 95, threadIdx.x) == 0;
    return r;
}

template <bool BY_SM> __global__ void __cluster_dims__(2, 1, 1) __launch_bounds__(512, 1)
fused_kernel(const __grid_constant__ CUtensorMap tmX, const __grid_constant__ CUtensorMap tmBre, const __grid_constant__ CUtensorMap tmBim,
             const __grid_constant__ CUtensorMap tmCre, const __grid_constant__ CUtensorMap tmCim, const __grid_constant__ CUtensorMap tmXd,
             const __grid_constant__ CUtensorMap tmUst,
             const __grid_constant__ CUtensorMap tmWr, const __grid_constant__ CUtensorMap tmWi, const __grid_constant__ CUtensorMap tmXa,
             const Params p) {
    extern __shared__ __align__(1024) uint8_t smraw[];
    asm volatile(".reg .pred pk, p0;");
    const int tid = TIDMAP, rank = blockIdx.x & 1;
    const uint32_t wi = __shfl_sync(~0u, smem_u32(smraw) + (tid >> 5), 0), sb = wi & ~15u, bars = sb + OFF_BAR;
    const int wg = (wi >> 2) & 3, w = wi & 3, lane = tid & 31, g = lane >> 2, q = lane & 3;
    if (wg != 3) asm volatile("barrier.cluster.arrive.relaxed.aligned; barrier.cluster.wait.aligned;" ::: "memory");
    else asm volatile("prefetch.tensormap [%0];" ::"l"(w == 0 ? &tmX : w == 1 ? &tmBre : &tmBim) : "memory");
    int role;
    {
        uint32_t T = blockIdx.x;
        if (BY_SM) asm("mov.u32 %0, %%smid;" : "=r"(T));
        T >>= 1;
        const uint32_t a = ((T - 32) * 37) >> 8;
        asm("{.reg .pred p; setp.lt.u32 p, %1, 62; selp.u32 %0, 4, -58, p; add.u32 %0, %0, %1;\n"
            "setp.lt.u32 p, %1, 60; selp.u32 %0, %2, %0, p; setp.lt.u32 p, %1, 32; selp.u32 %0, %3, %0, p;}"
            : "=&r"(role) : "r"(T), "r"(8 * (T - 31 - 7 * a) + 4 + a), "r"(8 * (T & 7) + (T >> 3)));
        role = 2 * role + rank;
    }
    const bool spare = role >= 128;
    const int tc = ((role >> 3) & 14) + rank, cb = (role >> 1) & 7;
    const int fb = role >> 5, fcb = role & 31, fpos = pos_of(fcb);
    const int nu = role == 128 ? 1 : (fcb || !role ? 2 : 0);

    if (wg == 3) {
        if (elect_one()) {
            const uint32_t b = bars + w * 8;
            STAMP5(57);
            mbar_init(b, 1);
            if (w < 2 && !spare) {
                mbar_expect_tx(b, 32768);
                tma5d(sb + w * 32768 + 16384, &tmX, w * 64, 0, 0, 0, tc, b);
                if (w == 0) { tma4d(sb, &tmBre, 0, 0, 0, cb * 4, b); tma4d(sb + 8192, &tmBim, 0, 0, 0, cb * 4, b); }
                STAMP5(58);
            }
#pragma unroll
            for (int o = 32; o < B_EPOCH; o += 32) mbar_init(b + o, o < B_EMPTY ? 1 : (o < B_STG ? 2 : (o < B_P3M ? 4 : 8)));
            asm volatile("fence.mbarrier_init.release.cluster;" ::: "memory");
        }
        __syncwarp();
        STAMP5(59);
        asm volatile("barrier.cluster.arrive.relaxed.aligned;" ::: "memory");
    }
    if (opaque32(wg) == 3) {
        asm volatile("setmaxnreg.dec.sync.aligned.u32 24;");
        asm volatile("barrier.cluster.wait.aligned;" ::: "memory");
        if (w == 0) {
            if (!spare && elect_one()) {
                STAMP(56);
#pragma unroll 1
                for (int k = 1; k < NST; k++) {
                    if (k >= 2) mbar_expect_tx(bars + B_FULL + k * 8, 32768);
                    tma4d_mc(sb + k * 32768 + rank * 8192, rank ? &tmBim : &tmBre, k * 64, 0, 0, cb * 4, bars + B_FULL + k * 8);
                    if (k >= 2) tma5d(sb + k * 32768 + 16384, &tmX, k * 64, 0, 0, 0, tc, bars + B_FULL + k * 8);
                }
#define RING_WAIT "mbarrier.try_wait.parity.shared::cta.b64 p, [fb + 256], ph; @p bra GO;\n" \
                  "WAIT: mbarrier.try_wait.parity.shared::cta.b64 p, [fb + 256], ph; add.u32 n, n, 1; setp.gt.or.u32 p, n, 32768, p; @!p bra WAIT;\nGO:\n"
#define RING_NEXT "pmevent 1; add.u32 o, o, 8; setp.eq.u32 p, o, 40; selp.u32 o, 0, o, p; @p xor.b32 ph, ph, 1; add.u32 fb, %1, o; shl.b32 t, o, 12; add.u32 da, %0, t;\n"
                asm volatile("{.reg .b32 o, k, kk, c2, da, db, fb, ph, n, t; .reg .pred p;\n"
                             "mov.b32 o, 0; mov.b32 k, 320; mov.b32 kk, 320; mov.b32 c2, 0; mov.b32 ph, 0; mov.b32 n, 0; mov.b32 fb, %1; mov.b32 da, %0; mov.b32 db, %2;\n"
                             "LOOP:\n" RING_WAIT
                             "cp.async.bulk.tensor.5d.shared::cluster.global.mbarrier::complete_tx::bytes [da], [%3, {kk,0,0,0,%5}], [fb];\n"
                             "cp.async.bulk.tensor.4d.shared::cluster.global.mbarrier::complete_tx::bytes.multicast::cluster [db], [%4, {kk,0,c2,%6}], [fb], %7;\n"
                             "mbarrier.arrive.expect_tx.shared::cta.b64 _, [fb], 32768;\n" RING_NEXT
                             "add.u32 db, %2, t; add.u32 k, k, 64; and.b32 kk, k, 1023; shr.u32 c2, k, 9; and.b32 c2, c2, 2; setp.ne.u32 p, k, 2048; @p bra LOOP;}"
                             ::"r"(sb + 16384), "r"(bars + B_FULL), "r"(sb + rank * 8192), "l"(&tmX), "l"(rank ? &tmBim : &tmBre), "r"(tc), "r"(cb * 4), "h"((uint16_t)3) : "memory");
                asm volatile("{.reg .b32 o, k, kk, da, db, fb, hb, ph, n, t; .reg .b64 m, src; .reg .pred p;\n"
                             "mov.b32 o, 16; mov.b32 k, 0; mov.b32 kk, 0; mov.b32 ph, 1; mov.b32 n, 0; add.u32 fb, %1, 16; add.u32 hb, %1, 72; add.u32 da, %0, 65536; add.u32 db, %2, 65536;\n"
                             "mov.b64 m, %3; mov.b64 src, %5;\n"
                             "GROUP: add.u32 t, %8, k;\n"
                             "OWN: mbarrier.try_wait.parity.shared::cta.b64 p, [t], 0; add.u32 n, n, 1; setp.gt.or.u32 p, n, 32768, p; @!p bra OWN;\n"
                             "LOOP:\n" RING_WAIT
                             "cp.async.bulk.shared::cluster.global.mbarrier::complete_tx::bytes [da], [src], 16384, [hb];\n"
                             "cp.async.bulk.tensor.5d.shared::cluster.global.mbarrier::complete_tx::bytes.multicast::cluster [db], [m, {kk,0,0,0,%6}], [fb], %7;\n"
                             "mbarrier.expect_tx.shared::cta.b64 [fb], 16384; mbarrier.arrive.expect_tx.shared::cta.b64 _, [hb], 16384;\n" RING_NEXT
                             "add.u32 db, %2, t; add.u64 src, src, 16384; sub.u64 m, %4, m; add.u32 k, k, 1; shl.b32 kk, k, 5; and.b32 kk, kk, 0x7c0;\n"
                             "and.b32 t, k, 1; mad.lo.u32 hb, t, 8, fb; add.u32 hb, hb, o; add.u32 hb, hb, 40;\n"
                             "and.b32 t, k, 7; setp.ne.u32 p, t, 0; @p bra LOOP; setp.ne.u32 p, k, 32; @p bra GROUP;}"
                             ::"r"(sb), "r"(bars + B_FULL), "r"(sb + 16384 + rank * 8192), "l"(&tmCre), "l"((uint64_t)&tmCre + (uint64_t)&tmCim),
                               "l"(g_H + (size_t)tc * 32 * 16384), "r"(cb * 8 + rank * 4), "h"((uint16_t)3), "r"(bars + B_HOWN) : "memory");
            }
        } else if (opaque32(w) == 1) {
            const unsigned ep = ld_rlx(g_epoch + role * 8) + 1;
            __syncwarp();
            if (elect_one()) {
                asm volatile("st.relaxed.gpu.global.u32 [%0], %1;" ::"l"(g_epoch + role * 8), "r"(ep) : "memory");
                asm volatile("st.shared.u32 [%0], %1;" ::"r"(bars + B_EPOCH), "r"(ep) : "memory");
                mbar_arrive(bars + B_EP);
            }
            int slot;
            const int kap = unit_of(role, 0, slot), kap1 = unit_of(role, 1, slot);
            uint32_t lph = 0;
            if (!spare) mbar_wait(bars + B_STGU, 0);
            STAMP(21);
            const int c0 = fb * 2048 + fpos * 64;
            if (elect_one()) {
                if (!spare) {
#pragma unroll 1
                    for (int r = 4; r < 8; r++) bulk_st(g_X + r * (32 * 16384) + c0 * 2, sb + OFF_P + r * 4096, 128);
                    tma2d_st(&tmUst, c0, 0, sb + OFF_P);
                    bulk_commit();
                    tma2d_st(&tmUst, c0, 64, sb + OFF_P + 8192);
                    bulk_commit();
                    if (UHINT == 1) asm volatile("cp.async.bulk.wait_group.read 1;" ::: "memory");
                    if (UHINT < 2) red_hint(g_cnt);
                }
                mbar_expect_tx(bars + B_FG, 8192);
                bulk_ld(sb + OFF_F, (const uint8_t*)g_tab + TAB_FG, 8192, bars + B_FG);
            }
            STAMP(40);
#pragma unroll 1
            for (int e = 0; e < 4; e++) {
                if (e >= 2) {
                    if (e == nu) {
                        mbar_wait(bars + B_WFREE, 0);
                        if (elect_one()) load_w_rows(sb + OFF_WD, &tmWr, &tmWi, kap1, bars + B_WD);
                    }
                    if (e - 2 < nu) mbar_wait(bars + B_STG, e & 1);
                    STAMPO(23, e - 2);
                    if (e == 3 && !spare && elect_one()) {
                        mbar_expect_tx(bars + B_FG, 8192);
                        bulk_ld(sb + OFF_F, (const uint8_t*)g_tab + TAB_G + fb * 8192, 8192, bars + B_FG);
                    }
                }
                const uint32_t tg = e < 2 ? lane * 128 + ((((lane >> 1) & 2) ^ (lane & 3)) << 4) + (lane >> 3) * 4 : lane * 64 + (lane & 8) * 4 + (lane & 2) * 8 + (lane & 4) * 2;
                if (spare) {
                    if (e == 1) {
                        wait_cnt(g_cnt, 128 * ep);
                        STAMP(42);
#pragma unroll 1
                        for (int n = 0; n < 4096; n++) {
                            if (elect_one()) {
                                mbar_expect_tx(bars + B_LD, 8 * 16384);
#pragma unroll 1
                                for (int r = 0; r < 8; r++) bulk_ld(sb + r * 16384, g_X + (size_t)r * (32 * 16384), 16384, bars + B_LD);
                            }
                            mbar_wait(bars + B_LD, n & 1);
                            bool ok = true;
#pragma unroll 1
                            for (int r = 0; r < 8; r++) ok &= tags_ok<4096>(sb + r * 16384 + tg, ep);
                            if (ok) break;
                        }
                        if (elect_one()) mbar_arrive(bars + B_RAW);
                    }
                } else {
                    const uint32_t dst = sb + OFF_P + (e & 1) * 16384;
                    wait_cnt(g_cnt + e * 32, 128 * ep);
                    STAMPO(41, e == 2 ? -12 : e);
#pragma unroll 1
                    for (int n = 0; n < 4096; n++) {
                        if (elect_one()) {
                            bulk_wait_read();
                            mbar_expect_tx(bars + B_LD, 16384);
                            bulk_ld(dst, g_X + (size_t)(e < 2 ? role + e * 128 : 254 + (fb * 32 + fpos) * 2 + e) * 16384, 16384, bars + B_LD);
                            if (U1POS <= 0 && e + n == 0) {
                                if (U1POS < 0 && nu) load_w_rows(sb + OFF_WD, &tmWr, &tmWi, kap, bars + B_WD);
                                tma2d_st(&tmUst, c0, 128, dst + 16384); tma2d_st(&tmUst, c0, 192, dst + 24576); bulk_commit();
                                if (U1POS == -2) { bulk_wait_read(); red_hint(g_cnt + 32); }
                            }
                        }
                        mbar_wait(bars + B_LD, lph);
                        if (!e) STAMP3(49);
                        lph ^= 1;
                        if (tags_ok<4096>(dst + tg, ep) & tags_ok<4096>(dst + tg + (e & 2) * 1024, ep) & tags_ok<0>(dst + (e == 3 ? (lane & 1) * 8192 + 32 : 0), ep)) break;
                    }
                    if (elect_one()) mbar_arrive(bars + B_IN + e * 8);
                }
                if (e < 2 && elect_one()) {
                    if (e) prefetch_w_rows(&tmWr, &tmWi, kap1);
                    else {
                        if (U1POS < 0 ? spare : nu) load_w_rows(sb + OFF_WD, &tmWr, &tmWi, kap, bars + B_WD);
                        if (!spare && U1POS != -2) {
                            if (U1POS > 0) { tma2d_st(&tmUst, c0, 128, sb + OFF_P + 16384); bulk_commit(); tma2d_st(&tmUst, c0, 192, sb + OFF_P + 24576); bulk_commit(); }
                            if (U1POS == 2) asm volatile("cp.async.bulk.wait_group.read 1;" ::: "memory"); else bulk_wait_read();
                            red_hint(g_cnt + 32);
                        }
                    }
                }
            }
            if (!spare) {
                mbar_wait(bars + B_HOWN + 8, 0);
#pragma unroll 1
                for (int r = 0; r < 4; r++) {
                    if (r == 3) mbar_wait(bars + B_P3M, 0);
                    if (elect_one()) {
                        if (r == 0) { mbar_expect_tx(bars + B_XD, 24576 + 256); mbar_expect_tx(bars + B_XD + 8, 8192); bulk_ld(sb + OFF_LAM, p.dsk + cb * 128, 256, bars + B_XD); }
                        tma4d(sb + OFF_F + (3 - r) * 8192, &tmXd, 0, tc * 128 + 32 * (r & 1) + 16 * (r >> 1), 0, cb * 2, bars + B_XD + (r == 3) * 8);
                    }
                    __nanosleep(PACE_X);
                }
            }
        } else {
            if (w == 2) {
                {
                    const int u = lane >> 4;
                    int slot;
                    const int r0 = unit_of(role, u, slot) + 512 * ((lane >> 1) & 3), r1 = (2048 - r0) & 2047, mir = (lane >> 3) & 1;
                    const unsigned short* wp = (const unsigned short*)((lane & 1) ? p.wi : p.wr);
                    const float a = bf2f(wp[r0 * 513 + mir * 512]), b = bf2f(wp[r1 * 513 + mir * 512]);
                    asm volatile("st.shared.f32 [%0], %1;" ::"r"(sb + OFF_WSP + u * 64 + (lane & 15) * 4), "f"(0.5f * ((lane & 1) ? (mir ? b - a : a - b) : a + b)) : "memory");
                }
                warp_arrive(bars + B_WSP);
            } else if (!spare) {
                if (XA_T0) __nanosleep(XA_T0);
#pragma unroll 1
                for (int i = 0; i < 8; i++) {
                    if (i >= XA_N0) __nanosleep(XA_PACE);
                    if (elect_one()) {
                        const uint32_t xb = bars + (P1H && i < 4 ? B_RAW : B_XIN);
                        if (P1H ? !(i & 3) : !i) mbar_expect_tx(xb, P1H ? 16384 : 32768);
                        tma3d(sb + OFF_F + i * 4096, &tmXa, fcb * 32, 0, 4 * i + fb, xb);
                    }
                }
            }
            if (!spare) {
                if (w == 2 && nu) {
                    int slot;
                    const int kap = unit_of(role, 0, slot);
                    mbar_wait(bars + WPFB, 0);
                    if (elect_one()) prefetch_w_rows(&tmWr, &tmWi, kap);
                }
                const unsigned ep = get_epoch(bars);
#define CNT_RETRY
#define CNT_ARG
                asm volatile("{.reg .b32 o, k, hb, fb, ca, m, ph, rph, n, t, v0, v1, v2, v3; .reg .b64 src; .reg .pred p, pe;\n"
                             "elect.sync _|pe, 0xffffffff; mov.b32 o, %0; shr.u32 k, %0, 3; sub.u32 k, k, 2; mov.b32 m, 0x107c0; mov.b32 rph, 0; mov.b32 n, 0;\n"
                             "bra NEXT;\n"
                             "LOOP: mbarrier.try_wait.parity.shared::cta.b64 p, [hb], ph; @p bra GO;\n"
                             "WAIT: mbarrier.try_wait.parity.shared::cta.b64 p, [hb], ph; add.u32 n, n, 1; setp.gt.or.u32 p, n, 32768, p; @!p bra WAIT;\n"
                             "GO: ld.shared.u32 v0, [ca]; ld.shared.u32 v1, [ca + 128]; ld.shared.u32 v2, [ca + 256]; ld.shared.u32 v3, [ca + 384];\n"
                             "lop3.b32 v0, v0, v1, %4, 0x7e; lop3.b32 v2, v2, v3, %4, 0x7e; lop3.b32 v0, v0, v2, 1, 0xa8; setp.eq.u32 p, v0, 0; vote.sync.all.pred p, p, -1; @p bra OK;\n"
                             CNT_RETRY "add.u32 n, n, 16; setp.gt.u32 p, n, 32768; @p bra OK;\n"
                             "shl.b32 t, o, 12; add.u32 t, t, %5; mad.wide.u32 src, k, 16384, %6;\n"
                             "@pe mbarrier.arrive.expect_tx.shared::cta.b64 _, [%7], 16384; @pe cp.async.bulk.shared::cluster.global.mbarrier::complete_tx::bytes [t], [src], 16384, [%7];\n"
                             "AGAIN: mbarrier.try_wait.parity.shared::cta.b64 p, [%7], rph; add.u32 n, n, 1; setp.gt.or.u32 p, n, 32768, p; @!p bra AGAIN;\n"
                             "xor.b32 rph, rph, 1; bra GO;\n"
                             "OK: @pe mbarrier.arrive.shared::cta.b64 _, [fb]; pmevent 1;\n"
                             "add.u32 o, o, 16; setp.ge.u32 p, o, 40; @p sub.u32 o, o, 40; add.u32 k, k, 2;\n"
                             "NEXT: shr.u32 m, m, 1; and.b32 ph, m, 1; add.u32 fb, %1, o; mad.lo.u32 hb, o, 2, %2; mad.lo.u32 ca, o, 4096, %3; setp.lt.u32 p, k, 32; @p bra LOOP;}"
                             ::"r"(8 * w), "r"(bars + B_FULL), "r"(bars + B_HL - 16 + w * 8), "r"(sb + (q >> 1) * 8192 + (q & 1) * 512 + g * 1040 + q * 4), "r"(ep),
                               "r"(sb), "l"(g_H + (size_t)tc * 32 * 16384), "r"(bars + B_HR - 16 + w * 8) CNT_ARG : "memory");
                if (w == 3) warp_arrive(bars + B_DONE);
            }
        }
    } else {
        STAMP(55);
        asm volatile("setmaxnreg.inc.sync.aligned.u32 152;");
        STAMP5(60);
        const int t7 = tid & 127, hf = wg - 1;
        const int mi = lane >> 3, gl = lane & 7;
        if (spare && wg != 2) {
            if (tid < 64) { const uint4 v = __ldg((const uint4*)((const uint8_t*)g_tab + TAB_PC) + tid); sts128(sb + OFF_LAM + tid * 16, v.x, v.y, v.z, v.w); }
            bar_sync(1, 256);
            mbar_wait(bars + B_RAW, 0);
            STAMP(0);
#pragma unroll 1
            for (int u = 0; u < nu; u++) {
                int slot;
                const int t = unit_of(role, u, slot) >> 5;
                const uint32_t off = (tid >> 2) * 128 + q * 16;
                float zr[16], zi[16];
#pragma unroll
                for (int k = 0; k < 16; k++) zr[k] = zi[k] = 0.f;
#pragma unroll 1
                for (int r = (t & 1) ? 0 : t >> 1; r < 8 - ((t & 1) ? 0 : (t >> 1) - 1); r += (t & 1) ? 1 : 8 - t) {
                    float4 c;
                    float a[8], b[8];
                    lds128f(sb + OFF_LAM + t * 128 + r * 16, c.x, c.y, c.z, c.w);
                    lds128f(sb + r * 16384 + off, a[0], a[1], a[2], a[3]);
                    lds128f(sb + r * 16384 + off + 64, b[0], b[1], b[2], b[3]);
                    lds128f(sb + r * 16384 + off + 8192, a[4], a[5], a[6], a[7]);
                    lds128f(sb + r * 16384 + off + 8192 + 64, b[4], b[5], b[6], b[7]);
#pragma unroll
                    for (int k = 0; k < 16; k++) {
                        const uint32_t ua = __float_as_uint(a[k >> 1]), ub = __float_as_uint(b[k >> 1]);
                        const float x = __uint_as_float((k & 1) ? ua & 0xffff0000u : ua << 16), y = __uint_as_float((k & 1) ? ub & 0xffff0000u : ub << 16);
                        zr[k] = fmaf(c.x, x, fmaf(c.z, y, zr[k]));
                        zi[k] = fmaf(c.y, x, fmaf(c.w, y, zi[k]));
                    }
                }
                const uint32_t dst = sb + OFF_P + u * 16384 + off;
#pragma unroll
                for (int k = 0; k < 16; k += 8) {
                    sts128(dst + k * 1024, pk(zr[k], zr[k + 1]), pk(zr[k + 2], zr[k + 3]), pk(zr[k + 4], zr[k + 5]), pk(zr[k + 6], zr[k + 7]));
                    sts128(dst + k * 1024 + 64, pk(zi[k], zi[k + 1]), pk(zi[k + 2], zi[k + 3]), pk(zi[k + 4], zi[k + 5]), pk(zi[k + 6], zi[k + 7]));
                }
                fence_async_sm();
                bar_sync(1, 256);
                if (tid == 0) mbar_arrive(bars + B_IN + u * 8);
                STAMPO(1, u);
            }
            return;
        }
        if (wg == 2 && !spare) {
            asm volatile("setmaxnreg.inc.sync.aligned.u32 176;");
            uint32_t f1[16];
            cf tw[8];
            if (TAB_T0) __nanosleep(TAB_T0);
            ldtab<4, 2048>(f1, TAB_F1 + t7 * 16);
            ldtab_cf<16>(tw, TAB_TW1 + (t7 >> 2) * 64);
            const uint32_t ep = get_epoch(bars);
            uint32_t a0 = sb + OFF_P + (8 * w + gl + 32 * (mi >> 1)) * 128 + (((((mi & 1) << 2) | (fpos & 3)) ^ gl) << 4);
            float acc[128];
            const uint64_t dx = opaque(mkdesc(sb + OFF_F, 4096, 512, 2));
            mbar_wait(bars + (P1H ? B_RAW : B_XIN), 0);
            pinu(f1);
            wg_fence();
#pragma unroll
            for (int j = 0; j < 4; j++) mma128_rs<0, 1>(acc, f1[4 * j], f1[4 * j + 1], f1[4 * j + 2], f1[4 * j + 3], dx + j * 64, j);
            if (P1H) { wg_commit(); mbar_wait(bars + B_XIN, 0); wg_fence(); }
            STAMP(20);
#pragma unroll
            for (int j = 0; j < 4; j++) mma128_rs<64, 1>(acc, f1[4 * j], f1[4 * j + 1], f1[4 * j + 2], f1[4 * j + 3], dx + 1024 + j * 64, j);
            wg_commit();
            wg_wait<0>();
            pin(acc);
            pinu(f1);
#pragma unroll 1
            for (int h = 0;; h++) {
                const uint32_t tmask = 2 * q + h == fpos >> 2 ? ~1u : ~0u, tbit = ep & ~tmask;
#pragma unroll
                for (int cl = 0; cl < 2; cl++) {
                    c2 v[8];
#pragma unroll
                    for (int n = 0; n < 8; n++) {
                        const int i = 4 * (4 * n + cl);
                        v[n] = {{acc[i], acc[i + 2]}, {acc[i + 1], acc[i + 3]}};
                    }
                    dft8<true, YP1>(v, tw);
#pragma unroll
                    for (int r = 0; r < 8; r += 2) {
                        uint32_t o0 = pk(v[r].a.x, v[r].b.x), o1 = pk(v[r].a.y, v[r].b.y), o2 = pk(v[r + 1].a.x, v[r + 1].b.x), o3 = pk(v[r + 1].a.y, v[r + 1].b.y);
                        if (cl == 0) { o0 = (o0 & tmask) | tbit; o2 = (o2 & tmask) | tbit; }
                        stsm4((a0 ^ (cl << 4)) + r * 4096, o0, o1, o2, o3);
                    }
                }
                if (h) break;
                a0 ^= 32;
#pragma unroll
                for (int n = 0; n < 8; n++) {
                    asm volatile("mov.b32 %0, %8; mov.b32 %1, %9; mov.b32 %2, %10; mov.b32 %3, %11; mov.b32 %4, %12; mov.b32 %5, %13; mov.b32 %6, %14; mov.b32 %7, %15; pmevent 1;"
                                 : "=&f"(acc[16 * n]), "=&f"(acc[16 * n + 1]), "=&f"(acc[16 * n + 2]), "=&f"(acc[16 * n + 3]), "=&f"(acc[16 * n + 4]), "=&f"(acc[16 * n + 5]), "=&f"(acc[16 * n + 6]), "=&f"(acc[16 * n + 7])
                                 : "f"(acc[16 * n + 8]), "f"(acc[16 * n + 9]), "f"(acc[16 * n + 10]), "f"(acc[16 * n + 11]), "f"(acc[16 * n + 12]), "f"(acc[16 * n + 13]), "f"(acc[16 * n + 14]), "f"(acc[16 * n + 15]));
                }
            }
            fence_async_sm();
            warp_arrive(bars + B_STGU);
            bar_sync(3, 128);
            asm volatile("setmaxnreg.dec.sync.aligned.u32 152;");
            bar_arrive(7, 256);
        }
        if (wg == 1) {
            if (LAM_T0) __nanosleep(LAM_T0);
            const int cl = tid & 127, ch = (cl >> 6) * 512 + ((cl >> 3) & 1) * 256 + cb * 32 + ((cl >> 4) & 3) * 8 + (cl & 7);
            const float lr = bf2f(*(const unsigned short*)padd(p.lre, 2 * ch)), li = bf2f(*(const unsigned short*)padd(p.lim, 2 * ch));
            const float dt = __bfloat162float(__float2bfloat16(expf(bf2f(*(const unsigned short*)padd(p.ldt, 2 * ch)))));
            const float an = dt * li, th = an * 0.318309873342514f;
            float sn, cs, inv;
            sincospif(fmaf(rintf(0.5f * th), -2.f, th) + fmaf(an, 1.2841276653e-8f, fmaf(an, 0.318309873342514f, -th)), &sn, &cs);
            const float ex = expf(dt * lr), br = ex * cs, bi = ex * sn;
            asm("rcp.approx.f32 %0, %1;" : "=f"(inv) : "f"(lr * lr + li * li));
            inv += inv;
            const float cr = ((br - 1.f) * lr + bi * li) * inv, ci = (bi * lr - (br - 1.f) * li) * inv;
            sts128(sb + OFF_LAM + cl * 16, __float_as_uint(br), __float_as_uint(-bi), __float_as_uint(cr), __float_as_uint(-ci));
            mbar_wait(bars + B_EP, 0);
            bar_sync(8, 128);
            if (tid == 128) mbar_arrive(bars + B_LAM);
        }
        if (wg != 2) {
        if (wg == 0) bar_sync(4, 128); else bar_sync(7, 256);
        asm volatile("setmaxnreg.inc.sync.aligned.u32 160;");
        if (wg == 0) bar_sync(4, 128);
        float d[128];
        STAMPW(0, 10);
        Ring rg = ring_at(sb, role * 66 + wg * 16);
        cf lam[2];
        unsigned ep;
        gemm1(d, rg, ring_desc(sb, 0, 16, 1), ring_desc(sb, 16384, 16, 1), wg);
        const uint32_t lama = sb + OFF_LAM + wg * 1024 + w * 256 + (fresh_lane() & 28) * 4;
        mbar_wait_fast(bars + B_LAM, 0);
        lam[0] = lds_cf(lama); lam[1] = lds_cf(lama + 128);
        asm volatile("ld.shared.u32 %0, [%1];" : "=r"(ep) : "r"(bars + B_EPOCH) : "memory");
        asm volatile("setmaxnreg.inc.sync.aligned.u32 176;");
        cf L[2] = {lam[0], lam[1]};
#pragma unroll
        for (int i = 0; i < 4; i++) { L[0] = csq(L[0]); L[1] = csq(L[1]); }
        asm volatile("" : "+f"(L[0].x), "+f"(L[0].y), "+f"(L[1].x), "+f"(L[1].y)::"memory");
        wg_wait<0>();
        ring_release(rg, 8 * wg);
        pin(d);
        STAMPW(1, 11);
        {
            const int lane = fresh_lane(), g = lane >> 2, q = lane & 3, mi = lane >> 3, gl = lane & 7;
            cf f[2], fb2[2];
#pragma unroll
            for (int i = 0; i < 17; i++) {
#pragma unroll
                for (int h = 0; h < 2; h++) {
                    const int r = 4 * (i >> 1) + 2 * h + (i & 1), r2 = 32 + 4 * ((i - 1) >> 1) + 2 * h + ((i - 1) & 1);
                    if (i < 16) f[h] = i ? cfma(lam[h], f[h], {d[r], -d[64 + r]}) : cf{d[r], -d[64 + r]};
                    if (i > 0) fb2[h] = i > 1 ? cfma(lam[h], fb2[h], {d[r2], -d[64 + r2]}) : cf{d[r2], -d[64 + r2]};
                    if (i && (h || !(YS & 8))) YIELD_S1();
                }
            }
            const uint8_t* cbase = (const uint8_t*)g_carry + (tc * 16 + wg * 8 + cb) * 512 + w * 64;
            const uint8_t* cptr = padd(cbase, g * 8);
            const unsigned tag = ep & 15u;
#pragma unroll
            for (int h = 0; h < 2; h++) { f[h] = cfma(L[h], f[h], fb2[h]); L[h] = csq(L[h]); }
            cf s0[2], s1[2], s2[2];
#pragma unroll
            for (int h = 0; h < 2; h++) {
                s0[h] = {__shfl_sync(~0u, f[h].x, 0, 4), __shfl_sync(~0u, f[h].y, 0, 4)};
                s1[h] = {__shfl_sync(~0u, f[h].x, 1, 4), __shfl_sync(~0u, f[h].y, 1, 4)};
                s2[h] = {__shfl_sync(~0u, f[h].x, 2, 4), __shfl_sync(~0u, f[h].y, 2, 4)};
            }
#pragma unroll
            for (int h = 0; h < 2; h++) {
                s1[h] = cfma(L[h], s0[h], s1[h]);
                s2[h] = cfma(L[h], s1[h], s2[h]);
                f[h] = cfma(L[h], s2[h], f[h]);
                asm volatile("{.reg .pred p; .reg .b64 a; setp.eq.u32 p, %3, 3; mov.b64 a, {%1,%2}; @p st.relaxed.gpu.global.b64 [%0], a;}" ::"l"(cptr + h * 256),
                             "r"((__float_as_uint(f[h].x) & ~15u) | tag), "f"(f[h].y), "r"(q) : "memory");
            }
            STAMPX(2, 12);
            cf gam = lds_cf(lama + 8);
            cf st = csel(q & 2, csel(q & 1, s2[0], s1[0]), csel(q & 1, s0[0], {0.f, 0.f}));
            const cf st1 = csel(q & 2, csel(q & 1, s2[1], s1[1]), csel(q & 1, s0[1], {0.f, 0.f}));
            cptr = padd(cbase - 4 * 8192, (3 - mi) * 8192 + gl * 8);
            const int nprev = tc - 1 - mi;
            const uint8_t* hptr = padd(g_H + (size_t)(tc * 32 + wg * 16 + (cb & 6)) * 16384 + ((cb & 1) * 4 + w) * 1024, g * 64 + ((q ^ (g >> 1)) << 4));
            const uint32_t hm = 4 * (g & 1) + (q ^ (g >> 1)) == (cb & 1) * 4 + w ? ~1u : ~0u;
            float u[64];
            uint64_t fv[4] = {tag, tag, tag, tag};
            prescale<0>(u, d, gam);
            gather(fv, cptr, nprev);
#pragma unroll 1
            for (int h = 0;; h++) {
                const cf L2 = csq(L[0]), M = csq(L2);
                cf M4 = csq(csq(M));
                M4 = {__shfl_sync(~0u, M4.x, 4 * gl), __shfl_sync(~0u, M4.y, 4 * gl)};
                cf lq = cmul(gam, cmul(csel(q & 1, L[0], {1.f, 0.f}), csel(q & 2, L2, {1.f, 0.f})));
                st = cmul(gam, st);
                asm volatile("pmevent 1;" : "+f"(lq.x), "+f"(lq.y), "+f"(st.x), "+f"(st.y));
#pragma unroll 1
                for (unsigned n = 0; __any_sync(~0u, (((uint32_t)fv[0] ^ tag) | ((uint32_t)fv[1] ^ tag) | ((uint32_t)fv[2] ^ tag) | ((uint32_t)fv[3] ^ tag)) & 15u) && n < SPIN_LIMIT; n++) gather(fv, cptr, nprev);
                if (!h) STAMPX(53, 54);
                cf P = as_cf(fv[3]), pj[4];
#pragma unroll
                for (int a = 2; a >= 0; a--) P = cfma(M4, P, as_cf(fv[a]));
                cptr += 256;
                asm volatile("" : "+f"(P.x), "+f"(P.y)::"memory");
                gather(fv, cptr, h ? -1 : nprev);
#pragma unroll
                for (int j = 3; j >= 0; j--) pj[j] = {__shfl_sync(~0u, P.x, g + 8 * j), __shfl_sync(~0u, P.y, g + 8 * j)};
                st = cfma(lq, cfma(M, cfma(M, cfma(M, pj[3], pj[2]), pj[1]), pj[0]), st);
                if (!h) STAMPX(3, 13);
                uint32_t keep = sb >> 28;
                scan2(u, lam[0], st, hptr, hm, ep & ~hm, keep);
                warp_arrive(bars + B_HOWN + wg * 16 + h * 8 + keep);
                if (h) break;
                STAMPW(4, 14);
                lds128f(lama + 128, lam[0].x, lam[0].y, gam.x, gam.y);
                st = st1;
                L[0] = L[1];
                hptr += 8 * 16384;
                prescale<1>(u, d, gam);
            }
            STAMPW(5, 15);
        }
        if (wg == 0) bar_sync(4, 128); else bar_sync(8, 128);
        if (wg == 0) {
            asm volatile("setmaxnreg.dec.sync.aligned.u32 160;");
            float y[128];
            rg = ring_at(sb, role * 66 + 32);
            STAMP(6);
            STAMP(7);
            const uint64_t dA = ring_desc(sb, 0, 512, 2), dB = ring_desc(sb, 16384, 16, 1);
            gemm2(y, rg, dA, dB, 0);
            asm volatile("setmaxnreg.inc.sync.aligned.u32 184;");
            const int lane = fresh_lane(), g = lane >> 2, q = lane & 3;
            const int pg = 2 * (g & 3) + (g >> 2);
            float* op = (float*)padd(p.out + (size_t)(tc * 128 + 64 * (w & 1) + 8 * (w >> 1)) * 2048 + 1024 + cb * 128, pg * 8192 + q * 16);
            const uint32_t xa = sb + OFF_F + (16 * (w & 1) + 8 * (w >> 1) + pg) * 128 + (((q >> 1) ^ pg) << 4) + (q & 1) * 8;
#define HALF0(k) wg_fence(); peek(k < 63 ? rg.full + SL(k + 1) * 8 : bars + B_XD, PH(k + 1)); half_step<0, k>(y, dA, dB); wg_commit(); peek_wait(k < 63 ? rg.full + SL(k + 1) * 8 : bars + B_XD, PH(k + 1), rg.n);
            HALF0(60) HALF0(61) HALF0(62) HALF0(63)
            const uint64_t dB2 = ring_desc(sb >> 1, 16384, 16, 1);
            uint32_t xa0[8], xa1[8], dd[16];
#pragma unroll
            for (int i = 0; i < 8; i++) asm volatile("ld.shared.v2.b32 {%0,%1}, [%2];" : "=r"(dd[2 * i]), "=r"(dd[2 * i + 1]) : "r"(sb + OFF_LAM + q * 8 + 32 * i) : "memory");
            load_x4<0, 0>(xa0, xa);
            wg_fence();
            half_step<64, 64 - SKEW>(y, dA, dB2);
            wg_commit();
            wg_wait<1>();
#pragma unroll
            for (int i = 0; i < 64; i++) asm volatile("" : "+f"(y[i])::"memory");
            STAMP(16);
#define M1(n) if (4 + (n) < 4 * SKEW) mma_h<64, 65 - SKEW + (n) / 4, (n) % 4>(y, dA, dB2);
#define MM(n) if (4 + (n) / 2 * MPP < 4 * SKEW) { if (MPY) YIELD(); wg_fence(); M1((n) / 2 * MPP) M1((n) / 2 * MPP + 1) if (MPP > 2) { M1((n) / 2 * MPP + 2) } }
#define OUT4(R, U, X, n) out_piece<R, U>(y, dd, X[0], X[1], op); MM(n) out_piece<R, U + 1>(y, dd, X[2], X[3], op); MM(n + 2) \
                         out_piece<R, U + 2>(y, dd, X[4], X[5], op); MM(n + 4) out_piece<R, U + 3>(y, dd, X[6], X[7], op); MM(n + 6)
            load_x4<0, 4>(xa1, xa);
            OUT4(0, 0, xa0, 0)
            load_x4<1, 0>(xa0, xa);
            OUT4(0, 4, xa1, 8)
            wg_commit();
            load_x4<1, 4>(xa1, xa);
            OUT4(1, 0, xa0, 16)
            load_x4<2, 0>(xa0, xa);
            OUT4(1, 4, xa1, 16)
            STAMP(18);
            wg_wait<0>();
#pragma unroll
            for (int i = 64; i < 128; i++) asm volatile("" : "+f"(y[i])::"memory");
            STAMP(8);
            load_x4<2, 4>(xa1, xa);
            mbar_wait_fast(bars + B_XD + 8, 0);
            OUT4(2, 0, xa0, 16)
            load_x4<3, 0>(xa0, xa);
            OUT4(2, 4, xa1, 16)
            load_x4<3, 4>(xa1, xa);
            OUT4(3, 0, xa0, 16)
            OUT4(3, 4, xa1, 16)
            STAMP(9);
            return;
        }
        asm volatile("setmaxnreg.dec.sync.aligned.u32 152;");
        } else {
        if (nu) {
            constexpr int Y = YP2;
            cf T[8];
            ldtab_cf<2048>(T, TAB_T + t7 * 16);
            const uint32_t ep = get_epoch(bars);
            const int ka = pos_of(t7 >> 2);
            asm volatile("setp.eq.u32 p0, %0, 0;" ::"r"(__shfl_sync(~0u, t7, lane)));
            mbar_wait(bars + B_WSP, 0);
            mbar_wait(bars + B_FG, 0);
            uint32_t wd[4], wm[4], vo[32];
            const uint8_t* vp;
            int slot;
            const int kap0 = unit_of(role, 0, slot), al = 2 * kap0;
            const int kap1 = __shfl_sync(~0u, unit_of(role, 1, slot), 0);
            slot = __shfl_sync(~0u, slot, 0);
            cf be1 = twid(kap0 + 512 * q, 2048), be2 = csq(be1), be3 = cmul(be1, be2);
#pragma unroll
            for (int j = 0; j < 4; j++) {
                wd[j] = sb + OFF_WD + ((j + q) & 3) * WPITCH + (al & 15) + 2 * ka + 64 * q;
                wm[j] = sb + OFF_WM + (((role ? 3 : 4) - j - q) & 3) * WPITCH + (-al & 15) + 1024 - 2 * ka - 64 * q;
                wd[j] = __shfl_sync(~0u, wd[j], lane);
            }
#pragma unroll 1
            for (int u = 0; u < nu; u++) {
                const uint32_t buf = sb + OFF_P + u * 16384;
                float acc[64], za[32], zb[32], ya[32], yb[32], vv[64];
                const uint64_t dF = opaque(mkdesc(sb + OFF_F, 16, 1024, 1)), dB = opaque(mkdesc(buf, 4096, 512, 2));
                mbar_wait(bars + B_IN + u * 8, 0);
                if (!role) {
                    const uint32_t z = buf + w * 1024 + (fresh_lane() >> 2) * 128 + 64 + (fresh_lane() & 3) * 16;
#pragma unroll
                    for (int i = 0; i < 4; i++) sts128(z + i * 4096, 0, 0, 0, 0);
                    fence_async_sm();
                    bar_sync(3, 128);
                }
                STAMP3(22);
                wg_fence();
#pragma unroll
                for (int j = 0; j < 4; j++) mma128_ss<0, 0, 1>(acc, dF + j * 2, dB + j * 64, j);
                wg_commit();
                if (u) {
                    warp_arrive(bars + B_STG);
                    store_v<0, 16>(vo, vp, role || !(fresh_lane() & 4));
                    hint_v(g_cnt + 64, role);
                    if (!role) { const uint32_t t = wm[0]; wm[0] = wm[1]; wm[1] = wm[2]; wm[2] = wm[3]; wm[3] = t; }
                }
                STAMP3(39);
                wg_wait<0>();
                pin(acc);
                STAMP3(30);
                uint32_t af[16], ag[16];
#pragma unroll
                for (int k = 0; k < 8; k++) {
                    uint32_t(&o)[16] = k < 4 ? af : ag;
                    const int c = k & 3;
#pragma unroll
                    for (int b = 0; b < 2; b++) {
                        const int i = 4 * (4 * ((k >> 2) * 2 + b) + c);
                        c2 x = mul2(c2{{acc[i], acc[i + 2]}, {acc[i + 1], acc[i + 3]}}, c2{T[2 * c], T[2 * c + 1]});
                        fin<Y>(x);
                        o[4 * c + b] = pk(x.a.x, x.a.y);
                        o[4 * c + 2 + b] = pk(x.b.x, x.b.y);
                    }
                    asm volatile("" : "+r"(o[4 * c]), "+r"(o[4 * c + 1]), "+r"(o[4 * c + 2]), "+r"(o[4 * c + 3])::"memory");
                    wg_fence();
                    mma64_rs<0>(k < 4 ? za : zb, o[4 * c], o[4 * c + 1], o[4 * c + 2], o[4 * c + 3], dF + c * 2, c);
                    if (YT && k < 7) YIELD();
                }
                wg_commit();
                STAMP3(31);
                mbar_wait(bars + B_WD, u & 1);
                uint32_t wr[16];
#pragma unroll
                for (int i = 0; i < 16; i++) wr[i] = lds16(wd[i >> 2] + 256 * ((i >> 1) & 1) + (i & 1) * 4 * WPITCH);
                wg_wait<0>();
                pin(za);
                pin(zb);
                pinu(af);
                pinu(ag);
                STAMP3(32);
#pragma unroll
                for (int jb = 0; jb < 4; jb++) {
                    const int i = 8 * jb;
                    c2 s0 = {{za[i], za[i + 4]}, {za[i + 1], za[i + 5]}}, s2 = {{za[i + 2], za[i + 6]}, {za[i + 3], za[i + 7]}};
                    c2 s1 = {{zb[i], zb[i + 4]}, {zb[i + 1], zb[i + 5]}}, s3 = {{zb[i + 2], zb[i + 6]}, {zb[i + 3], zb[i + 7]}};
                    s2 = mul2(s2, be1);
                    fin<Y>(s2);
                    bfly_tw<Y>(s0, s1, be2, s2, s3, be3);
                    bfly<Y>(s0, s2); bfly_mi<Y>(s1, s3);
                    c2 W[4];
#pragma unroll
                    for (int j = 0; j < 4; j++) {
                        W[j] = {{__uint_as_float(wr[4 * j] << 16), __uint_as_float(wr[4 * j + 1] << 16)}, {__uint_as_float(wr[4 * j + 2] << 16), __uint_as_float(wr[4 * j + 3] << 16)}};
                        if ((jb & 1) == 0)
                            asm volatile("@p0 ld.shared.v2.f32 {%0,%1}, [%2];" : "+f"(W[j].a.x), "+f"(W[j].a.y) : "r"(sb + OFF_WSP + u * 64 + jb * 16 + j * 8));
                    }
                    if (jb < 3) {
#pragma unroll
                        for (int k = 0; k < 16; k++) {
                            const int e = (k >> 1) & 1, pl = (k & 1) * 4 * WPITCH;
                            wr[k] = jb == 0 ? lds16(wd[k >> 2] + 512 + 256 * e + pl) : lds16(wm[k >> 2] - 512 * (jb - 1) - 256 * e + pl);
                        }
                    }
                    if (jb >= 2) {
#pragma unroll
                        for (int j = 0; j < 4; j++) { W[j].a.y = -W[j].a.y; W[j].b.y = -W[j].b.y; }
                    }
                    s0 = mul2(s0, W[0]); fin<Y>(s0);
                    s1 = mul2(s1, W[1]); fin<Y>(s1);
                    bfly_tw<Y>(s0, s2, W[2], s1, s3, W[3]);
                    bfly<Y>(s0, s1); bfly_mi<Y>(s2, s3);
                    af[4 * jb] = pk(s0.a.x, s0.b.x); af[4 * jb + 1] = pk(s3.a.x, s3.b.x); af[4 * jb + 2] = pk(s0.a.y, s0.b.y); af[4 * jb + 3] = pk(s3.a.y, s3.b.y);
                    ag[4 * jb] = pk(s1.a.x, s1.b.x); ag[4 * jb + 1] = pk(s2.a.x, s2.b.x); ag[4 * jb + 2] = pk(s1.a.y, s1.b.y); ag[4 * jb + 3] = pk(s2.a.y, s2.b.y);
                }
                pinu(af);
                pinu(ag);
                warp_arrive(bars + B_WFREE);
                wg_fence();
#pragma unroll
                for (int j = 0; j < 4; j++) mma64_rs<1>(ya, af[4 * j], af[4 * j + 1], af[4 * j + 2], af[4 * j + 3], dF + j * 128, j);
                wg_commit();
#pragma unroll
                for (int j = 0; j < 4; j++) mma64_rs<1>(yb, ag[4 * j], ag[4 * j + 1], ag[4 * j + 2], ag[4 * j + 3], dF + j * 128, j);
                wg_commit();
                STAMP3(33);
                {
                    const uint32_t a0 = buf + (mi & 1) * 4096 + (16 * w + 8 * (mi >> 1) + gl) * 64 + ((gl >> 1) << 4);
#pragma unroll
                    for (int h = 0; h < 2; h++) {
                        if (h == 0) { wg_wait<1>(); pin(ya); pinu(af); STAMP3(34); } else { wg_wait<0>(); pin(yb); pinu(ag); }
                        const float(&yy)[32] = h ? yb : ya;
#pragma unroll
                        for (int c = 0; c < 4; c++) {
                            const int i = 8 * ((c + 2 * h) & 3), k = 8 * ((c + 2 * h + 1) & 3) + 2;
                            c2 x = {cmulc({yy[i], yy[i + 1]}, T[2 * c]), cmulc({yy[k], yy[k + 1]}, T[2 * c])};
                            fin<Y>(x);
                            c2 y = {cmulc({yy[i + 4], yy[i + 5]}, T[2 * c + 1]), cmulc({yy[k + 4], yy[k + 5]}, T[2 * c + 1])};
                            fin<Y>(y);
                            stsm4((a0 ^ (c << 4)) + h * 8192, pk(x.a.x, y.a.x), pk(x.b.x, y.b.x), pk(x.a.y, y.a.y), pk(x.b.y, y.b.y));
                        }
                    }
                }
                STAMP3(38);
                fence_async_sm();
                bar_sync(3, 128);
                wg_fence();
#pragma unroll
                for (int j = 0; j < 4; j++) mma128_ss<0, 1, 1>(vv, dF + j * 128, dB + j * 64, j);
                wg_commit();
                STAMP3(35);
                const int lane = fresh_lane(), g = lane >> 2, q = lane & 3;
                vp = padd(g_X + (4 << 20) + w * (8 * 32768) + (role ? u : 1) * 16384 + slot * 64,
                                         (g >> 1) * 32768 + (role ? g & 1 : u) * 32 + (((q ^ (slot >> 1)) & 1) << 4) + (q >> 1) * 8);
                const uint32_t tmask = (((g & 1) == ((slot >> 3) & 1) || !role) && q == ((slot >> 1) & 2)) ? ~1u : ~0u, tbit = ep & ~tmask;
                be1 = twid(kap1 + 512 * q, 2048); be2 = csq(be1); be3 = cmul(be1, be2);
                asm volatile("pmevent 1;" : "+f"(be1.x), "+f"(be1.y), "+f"(be2.x), "+f"(be2.y), "+f"(be3.x), "+f"(be3.y), "+l"(vp)::"memory");
                wg_wait<0>();
                pin(vv);
                STAMP3(36);
#pragma unroll
                for (int k = 0; k < 16; k++) {
                    const int i = 8 * (k >> 1) + 2 * (k & 1);
                    vo[2 * k] = (pk(vv[i], vv[i + 1]) & tmask) | tbit;
                    vo[2 * k + 1] = pk(vv[i + 4], vv[i + 5]);
                }
                pinu(vo);
            }
            warp_arrive(bars + B_STG);
            const bool odd = fresh_lane() & 4;
            if (!VPOS) hint_v(g_cnt + 32 + nu * 32, 1);
            store_v<0, 4>(vo, vp, role || !odd);
            if (VPOS) hint_v(g_cnt + 32 + nu * 32, 1);
            store_v<4, 16>(vo, vp, role || odd);
        }
        if (spare) return;
        }
        {
            constexpr int Y = YP3;
            uint32_t sp[8];
            cf tw[8];
            ldtab<2, 2048>(sp, TAB_SP + fb * 4096 + t7 * 16);
            ldtab_cf<16>(tw, TAB_TW3 + fb * 2048 + (t7 >> 2) * 64);
            const uint64_t dF = opaque(mkdesc(sb + OFF_F, 16, 1024, 1)), dB = opaque(mkdesc(sb + OFF_P + hf * 8192, 1024, 256, 3));
            const uint8_t* op = padd(p.out + (1024 + fb) * 2048 + fcb * 32 + hf * 16, (t7 >> 2) * 32768 + (q >> 1) * 16 + (q & 1) * 32);
            float acc[64], out[64];
            mbar_wait(bars + B_IN + 24, 0);
            mbar_wait(bars + B_FG, 1);
            STAMP(25);
            pinu(sp);
            wg_fence();
#pragma unroll
            for (int j = 0; j < 4; j++) {
                const uint64_t db = dB + (j >> 1) * 1024 + (j & 1) * 32;
                mma112_ss(acc, dF + j * 2, db + 64, j);
                if (j & 1) mma16_rs(acc, 0u, sp[2 * j], 0u, sp[2 * j + 1], db, 1);
                else mma16_rs(acc, sp[2 * j], 0u, sp[2 * j + 1], 0u, db, j);
            }
            wg_commit();
            wg_wait<0>();
            pin(acc);
            pinu(sp);
            warp_arrive(bars + B_P3M);
            if (STAG && !hf) bar_sync(5, 256);
#pragma unroll
            for (int cl = 0; cl < 2; cl++) {
                c2 z[8];
#pragma unroll
                for (int n = 0; n < 8; n++) {
                    const int i = 4 * (2 * n + cl);
                    z[n] = {{acc[i], acc[i + 2]}, {acc[i + 1], acc[i + 3]}};
                }
                z[0] = {{z[0].a.x + z[0].a.y, z[0].a.x - z[0].a.y}, {z[0].b.x + z[0].b.y, z[0].b.x - z[0].b.y}};
                z[4] = mul2(z[4], tw[4]);
                fin<Y>(z[0], z[4]);
#pragma unroll
                for (int n = 1; n < 4; n++) {
                    const cf iw = n == 1 ? cf{0.38268343236508977f, 0.92387953251128674f}
                                         : (n == 2 ? cf{0.70710678118654752f, 0.70710678118654752f} : cf{0.92387953251128674f, 0.38268343236508977f});
                    c2 y = mul2(z[n], tw[n]);
                    fin<Y>(y);
                    const cf t = {tw[8 - n].x, -tw[8 - n].y};
                    c2 E = fma2(c2{{z[8 - n].a.x, -z[8 - n].a.y}, {z[8 - n].b.x, -z[8 - n].b.y}}, t, y);
                    fin<Y>(E);
                    z[n] = fma2(twm2(y, E), iw, E);
                    fin<Y>(z[n]);
                    z[8 - n] = {{fmaf(2.f, E.a.x, -z[n].a.x), fmaf(-2.f, E.a.y, z[n].a.y)}, {fmaf(2.f, E.b.x, -z[n].b.x), fmaf(-2.f, E.b.y, z[n].b.y)}};
                }
                dft8<false, Y>(z, tw);
#pragma unroll
                for (int m = 0; m < 8; m++) {
                    out[8 * m + 2 * cl] = z[m].a.x; out[8 * m + 2 * cl + 1] = z[m].b.x;
                    out[8 * m + 4 + 2 * cl] = z[m].a.y; out[8 * m + 5 + 2 * cl] = z[m].b.y;
                }
            }
            pin(out);
            if (STAG) { if (hf) bar_arrive(5, 256); else if (STAG > 1) bar_sync(6, 256); }
            if (hf) STAMP(26);
#pragma unroll
            for (int m = 0; m < 16; m++) {
                asm volatile("st.global.v4.f32 [%0], {%1,%2,%3,%4};" ::"l"(op + (m - 8) * (1 << 20)), "f"(out[4 * m]), "f"(out[4 * m + 1]), "f"(out[4 * m + 2]), "f"(out[4 * m + 3]) : "memory");
                if (PACE_O && m < 15 && m % PACE_ON == PACE_ON - 1)
                    asm volatile("{.reg .pred p; mbarrier.test_wait.parity.shared::cta.b64 p, [%0], 0; @!p nanosleep.u32 %1;}" ::"r"(bars + B_DONE), "n"(PACE_O) : "memory");
            }
            if (STAG > 1 && hf) bar_arrive(6, 256);
            STAMP(27);
        }
    }
}

typedef CUresult (*EncodeFn)(CUtensorMap*, CUtensorMapDataType, cuuint32_t, void*, const cuuint64_t*, const cuuint64_t*, const cuuint32_t*,
                             const cuuint32_t*, CUtensorMapInterleave, CUtensorMapSwizzle, CUtensorMapL2promotion, CUtensorMapFloatOOBfill);

static CUtensorMap make_map(EncodeFn enc, const void* ptr, int rank, const cuuint64_t* dims, const cuuint64_t* strides, const cuuint32_t* box,
                            CUtensorMapSwizzle swz, CUtensorMapL2promotion promo, CUtensorMapDataType dt = CU_TENSOR_MAP_DATA_TYPE_BFLOAT16) {
    CUtensorMap m;
    const cuuint32_t es[5] = {1, 1, 1, 1, 1};
    enc(&m, dt, rank, const_cast<void*>(ptr), dims, strides, box, es, CU_TENSOR_MAP_INTERLEAVE_NONE, swz, promo,
        CU_TENSOR_MAP_FLOAT_OOB_FILL_NONE);
    return m;
}

extern "C" void kernel_launch(void* const* d_in, const int* in_sizes, int n_in, void* d_out, int out_size) {
    void* fn = nullptr;
    cudaDriverEntryPointQueryResult qr;
    cudaGetDriverEntryPoint("cuTensorMapEncodeTiled", &fn, cudaEnableDefault, &qr);
    EncodeFn enc = (EncodeFn)fn;
    void* pX;
    cudaGetSymbolAddress(&pX, g_X);
    const CUtensorMapL2promotion P256 = CU_TENSOR_MAP_L2_PROMOTION_L2_256B, P0 = CU_TENSOR_MAP_L2_PROMOTION_NONE;

    const cuuint64_t dX[5] = {1024, 2, 4, 16, 16}, sX[4] = {2048, 32 * 2048, 2 * 2048, 128 * 2048};
    const cuuint32_t bX[5] = {64, 2, 4, 16, 1};
    CUtensorMap tmX = make_map(enc, d_in[3], 5, dX, sX, bX, CU_TENSOR_MAP_SWIZZLE_128B, P256);
    const cuuint64_t dXd[4] = {64, 2048, 2, 16}, sXd[3] = {2048, 64 * 2048, 128};
    const cuuint32_t bXd[4] = {64, 16, 2, 2};
    CUtensorMap tmXd = make_map(enc, d_in[3], 4, dXd, sXd, bXd, CU_TENSOR_MAP_SWIZZLE_128B, P256);
    const cuuint64_t dB[4] = {1024, 8, 4, 32}, sB[3] = {2048, 256 * 2048, 8 * 2048};
    const cuuint32_t bB4[4] = {64, 8, 2, 4};
    CUtensorMap tmBre = make_map(enc, d_in[6], 4, dB, sB, bB4, CU_TENSOR_MAP_SWIZZLE_128B, P256);
    CUtensorMap tmBim = make_map(enc, d_in[7], 4, dB, sB, bB4, CU_TENSOR_MAP_SWIZZLE_128B, P256);
    const cuuint64_t dC[5] = {1024, 2, 4, 2, 64}, sC[4] = {2048, 4 * 2048, 2 * 2048, 16 * 2048};
    const cuuint32_t bC[5] = {64, 2, 4, 2, 4};
    CUtensorMap tmCre = make_map(enc, d_in[8], 5, dC, sC, bC, CU_TENSOR_MAP_SWIZZLE_128B, P256);
    CUtensorMap tmCim = make_map(enc, d_in[9], 5, dC, sC, bC, CU_TENSOR_MAP_SWIZZLE_128B, P256);

    const cuuint64_t dU[2] = {8192, 256}, sU[1] = {16384};
    const cuuint32_t bU[2] = {64, 64};
    CUtensorMap tmUst = make_map(enc, pX, 2, dU, sU, bU, CU_TENSOR_MAP_SWIZZLE_128B, P0);
    const cuuint64_t dF[2] = {512 * 1026 / 8, 4}, sF[1] = {512 * 1026};
    const cuuint32_t bF[2] = {WPITCH / 8, 4};
    CUtensorMap tmWr = make_map(enc, d_in[1], 2, dF, sF, bF, CU_TENSOR_MAP_SWIZZLE_NONE, P0, CU_TENSOR_MAP_DATA_TYPE_UINT64);
    CUtensorMap tmWi = make_map(enc, d_in[2], 2, dF, sF, bF, CU_TENSOR_MAP_SWIZZLE_NONE, P0, CU_TENSOR_MAP_DATA_TYPE_UINT64);

    const cuuint64_t dA[3] = {1024, 64, 32}, sA[2] = {32 * 2048, 2048};
    const cuuint32_t bA[3] = {32, 64, 1};
    CUtensorMap tmXa = make_map(enc, d_in[0], 3, dA, sA, bA, CU_TENSOR_MAP_SWIZZLE_64B, XA_PROMO);

    Params p;
    p.wr = (const __nv_bfloat16*)d_in[1];
    p.wi = (const __nv_bfloat16*)d_in[2];
    p.lre = (const __nv_bfloat16*)d_in[4];
    p.lim = (const __nv_bfloat16*)d_in[5];
    p.ldt = (const __nv_bfloat16*)d_in[10];
    p.dsk = (const __nv_bfloat16*)d_in[11];
    p.out = (float*)d_out;
    int dev = 0, sms = 0;
    cudaGetDevice(&dev);
    cudaDeviceGetAttribute(&sms, cudaDevAttrMultiProcessorCount, dev);
    auto kernel = sms == 132 ? fused_kernel<true> : fused_kernel<false>;
    cudaFuncSetAttribute(kernel, cudaFuncAttributeMaxDynamicSharedMemorySize, SMEM_BYTES);
    kernel<<<132, 512, SMEM_BYTES>>>(tmX, tmBre, tmBim, tmCre, tmCim, tmXd, tmUst, tmWr, tmWi, tmXa, p);
}
```

```cpp
#include <cuda_runtime.h>
#include <cuda.h>
#include <cuda_bf16.h>
#include <stdint.h>

#define NST 5
#define WPITCH 1056
#define OFF_P (NST * 32768)
#define OFF_F (OFF_P + 32768)
#define OFF_WD (OFF_F + 8192)
#define OFF_WM (OFF_WD + 8 * WPITCH)
#define OFF_BAR (OFF_F + 32768)
#define OFF_LAM (OFF_BAR + 432)
#define OFF_WSP (OFF_LAM + 2048)
#define OFF_PROF (OFF_WSP + 128)
#define SMEM_BYTES OFF_PROF
#define B_FULL 0
#define B_HL 40
#define B_EP 120
#define B_HR 128
#define B_XD 144
#define B_FG 160
#define B_WSP 168
#define B_WD 176
#define B_DONE 184
#define B_LD 192
#define B_RAW 200
#define B_LAM 208
#define B_IN 216
#define B_XIN 248
#define B_EMPTY 256
#define B_STG 320
#define B_WFREE 328
#define B_HOWN 336
#define B_STGU 368
#define B_P3M 384
#define B_EPOCH 416

#define PACE_U 20
#define PACE_V 20
#define XA_PACE 200
#define XA_PACE2 100
#define XA_TAB 0
#define XA_TABP 200
#define PACE_O 200
#define PACE_ON 2
#define XA_PROMO CU_TENSOR_MAP_L2_PROMOTION_L2_128B
#define TAB_T0 500
#define LAM_T0 1000
#define DEFER 0
#define UHINT 1
#define VPOS 2
#define VPOS0 8
#define GOV_T 100
#define GOV_K0 16
#define GOV_N 22
#define TIDMAP threadIdx.x
#define U1POS 2
#define WPFB B_XIN
#define VS0 16
#define YT 1
#define MPP 2
#define MPY 0
#define STAG 1
#define P1H 1
#define YI 2
#define XW 3
#define XA_N0 2
#define XA_T0 0
#define PACE_X 200
#define SKEW 4
#define SPIN_LIMIT (1u << 15)

__device__ __align__(1024) uint8_t g_X[8 << 20];
__device__ __align__(1024) uint8_t g_H[8 << 20];
__device__ __align__(1024) uint4 g_carry[16 * 512];
__device__ __align__(128) unsigned g_cnt[128];
__device__ __align__(128) unsigned g_epoch[132 * 8];

#define STAMP(i) do { } while (0)
#define STAMPO(i, o) do { } while (0)
#define STAMPW(a, b) do { } while (0)
#define STAMPX(a, b) do { } while (0)
#define STAMP5(i) do { } while (0)
#define STAMP6(i) do { } while (0)
#define STAMP3(i) do { } while (0)

#define TAB_FG 0
#define TAB_G 8192
#define TAB_F1 40960
#define TAB_T 49152
#define TAB_SP 57344
#define TAB_TW1 73728
#define TAB_TW3 75776
#define TAB_PC 83968
__device__ __align__(1024) const uint32_t g_tab[21248] = {
0x80003d80,0x80003d80,0x80003d80,0x80003d80,0x80003d80,0x80003d80,0x80003d80,0x80003d80,0x80003d80,0x80003d80,0x80003d80,0x80003d80,0x80003d80,0x80003d80,0x80003d80,0x80003d80,
0x80003d80,0x80003d80,0x80003d80,0x80003d80,0x80003d80,0x80003d80,0x80003d80,0x80003d80,0x80003d80,0x80003d80,0x80003d80,0x80003d80,0x80003d80,0x80003d80,0x80003d80,0x80003d80,
0x3d353d35,0x3d35bd35,0xbd35bd35,0xbd353d35,0x80003d80,0x3d800000,0x8000bd80,0xbd800000,0x3d353d35,0x3d35bd35,0xbd35bd35,0xbd353d35,0x80003d80,0x3d800000,0x8000bd80,0xbd800000,
0x3d353d35,0x3d35bd35,0xbd35bd35,0xbd353d35,0x80003d80,0x3d800000,0x8000bd80,0xbd800000,0x3d353d35,0x3d35bd35,0xbd35bd35,0xbd353d35,0x80003d80,0x3d800000,0x8000bd80,0xbd800000,
0x3d800000,0x3d6dbcc4,0x3d35bd35,0x3cc4bd6d,0x3d7bbc48,0x3d55bd0e,0x3d0ebd55,0x3c48bd7b,0x80003d80,0x3cc43d6d,0x3d353d35,0x3d6d3cc4,0x3c483d7b,0x3d0e3d55,0x3d553d0e,0x3d7b3c48,
0xbd800000,0xbd6d3cc4,0xbd353d35,0xbcc43d6d,0xbd7b3c48,0xbd553d0e,0xbd0e3d55,0xbc483d7b,0x8000bd80,0xbcc4bd6d,0xbd35bd35,0xbd6dbcc4,0xbc48bd7b,0xbd0ebd55,0xbd55bd0e,0xbd7bbc48,
0x3d0ebd55,0xbd7bbc48,0x3c483d7b,0x3d55bd0e,0x3d800000,0xbcc4bd6d,0xbd353d35,0x3d6d3cc4,0x3d553d0e,0x3c48bd7b,0xbd7b3c48,0x3d0e3d55,0x80003d80,0x3d6dbcc4,0xbd35bd35,0xbcc43d6d,
0xbd0e3d55,0x3d7b3c48,0xbc48bd7b,0xbd553d0e,0xbd800000,0x3cc43d6d,0x3d35bd35,0xbd6dbcc4,0xbd55bd0e,0xbc483d7b,0x3d7bbc48,0xbd0ebd55,0x8000bd80,0xbd6d3cc4,0x3d353d35,0x3cc4bd6d,
0x80003d80,0x3d353d35,0x3d800000,0x3d35bd35,0x3cc43d6d,0x3d6d3cc4,0x3d6dbcc4,0x3cc4bd6d,0x8000bd80,0xbd35bd35,0xbd800000,0xbd353d35,0xbcc4bd6d,0xbd6dbcc4,0xbd6d3cc4,0xbcc43d6d,
0x80003d80,0x3d353d35,0x3d800000,0x3d35bd35,0x3cc43d6d,0x3d6d3cc4,0x3d6dbcc4,0x3cc4bd6d,0x8000bd80,0xbd35bd35,0xbd800000,0xbd353d35,0xbcc4bd6d,0xbd6dbcc4,0xbd6d3cc4,0xbcc43d6d,
0x3d6d3cc4,0xbcc4bd6d,0xbcc43d6d,0x3d6dbcc4,0x80003d80,0x3d35bd35,0xbd800000,0x3d353d35,0xbd6dbcc4,0x3cc43d6d,0x3cc4bd6d,0xbd6d3cc4,0x8000bd80,0xbd353d35,0x3d800000,0xbd35bd35,
0x3d6d3cc4,0xbcc4bd6d,0xbcc43d6d,0x3d6dbcc4,0x80003d80,0x3d35bd35,0xbd800000,0x3d353d35,0xbd6dbcc4,0x3cc43d6d,0x3cc4bd6d,0xbd6d3cc4,0x8000bd80,0xbd353d35,0x3d800000,0xbd35bd35,
0x3d800000,0x3cc4bd6d,0xbd35bd35,0xbd6d3cc4,0x3d55bd0e,0xbc48bd7b,0xbd7bbc48,0xbd0e3d55,0x8000bd80,0xbd6dbcc4,0xbd353d35,0x3cc43d6d,0xbd0ebd55,0xbd7b3c48,0xbc483d7b,0x3d553d0e,
0xbd800000,0xbcc43d6d,0x3d353d35,0x3d6dbcc4,0xbd553d0e,0x3c483d7b,0x3d7b3c48,0x3d0ebd55,0x80003d80,0x3d6d3cc4,0x3d35bd35,0xbcc4bd6d,0x3d0e3d55,0x3d7bbc48,0x3c48bd7b,0xbd55bd0e,
0x3c48bd7b,0xbd0e3d55,0x3d55bd0e,0xbd7b3c48,0x3d800000,0xbd6dbcc4,0x3d353d35,0xbcc4bd6d,0xbd7bbc48,0x3d553d0e,0xbd0ebd55,0x3c483d7b,0x8000bd80,0xbcc43d6d,0x3d35bd35,0xbd6d3cc4,
0xbc483d7b,0x3d0ebd55,0xbd553d0e,0x3d7bbc48,0xbd800000,0x3d6d3cc4,0xbd35bd35,0x3cc43d6d,0x3d7b3c48,0xbd55bd0e,0x3d0e3d55,0xbc48bd7b,0x80003d80,0x3cc4bd6d,0xbd353d35,0x3d6dbcc4,
0x3d800000,0x3d800000,0x3d800000,0x3d800000,0x3d800000,0x3d800000,0x3d800000,0x3d800000,0x3d800000,0x3d800000,0x3d800000,0x3d800000,0x3d800000,0x3d800000,0x3d800000,0x3d800000,
0x3d800000,0x3d800000,0x3d800000,0x3d800000,0x3d800000,0x3d800000,0x3d800000,0x3d800000,0x3d800000,0x3d800000,0x3d800000,0x3d800000,0x3d800000,0x3d800000,0x3d800000,0x3d800000,
0x3d35bd35,0xbd35bd35,0xbd353d35,0x3d353d35,0x3d800000,0xbd80,0xbd800000,0x3d80,0x3d35bd35,0xbd35bd35,0xbd353d35,0x3d353d35,0x3d800000,0xbd80,0xbd800000,0x3d80,
0x3d35bd35,0xbd35bd35,0xbd353d35,0x3d353d35,0x3d800000,0xbd80,0xbd800000,0x3d80,0x3d35bd35,0xbd35bd35,0xbd353d35,0x3d353d35,0x3d800000,0xbd80,0xbd800000,0x3d80,
0xbd80,0xbcc4bd6d,0xbd35bd35,0xbd6dbcc4,0xbc48bd7b,0xbd0ebd55,0xbd55bd0e,0xbd7bbc48,0x3d800000,0x3d6dbcc4,0x3d35bd35,0x3cc4bd6d,0x3d7bbc48,0x3d55bd0e,0x3d0ebd55,0x3c48bd7b,
0x3d80,0x3cc43d6d,0x3d353d35,0x3d6d3cc4,0x3c483d7b,0x3d0e3d55,0x3d553d0e,0x3d7b3c48,0xbd800000,0xbd6d3cc4,0xbd353d35,0xbcc43d6d,0xbd7b3c48,0xbd553d0e,0xbd0e3d55,0xbc483d7b,
0xbd55bd0e,0xbc483d7b,0x3d7bbc48,0xbd0ebd55,0xbd80,0xbd6d3cc4,0x3d353d35,0x3cc4bd6d,0x3d0ebd55,0xbd7bbc48,0x3c483d7b,0x3d55bd0e,0x3d800000,0xbcc4bd6d,0xbd353d35,0x3d6d3cc4,
0x3d553d0e,0x3c48bd7b,0xbd7b3c48,0x3d0e3d55,0x3d80,0x3d6dbcc4,0xbd35bd35,0xbcc43d6d,0xbd0e3d55,0x3d7b3c48,0xbc48bd7b,0xbd553d0e,0xbd800000,0x3cc43d6d,0x3d35bd35,0xbd6dbcc4,
0x3d800000,0x3d35bd35,0xbd80,0xbd35bd35,0x3d6dbcc4,0x3cc4bd6d,0xbcc4bd6d,0xbd6dbcc4,0xbd800000,0xbd353d35,0x3d80,0x3d353d35,0xbd6d3cc4,0xbcc43d6d,0x3cc43d6d,0x3d6d3cc4,
0x3d800000,0x3d35bd35,0xbd80,0xbd35bd35,0x3d6dbcc4,0x3cc4bd6d,0xbcc4bd6d,0xbd6dbcc4,0xbd800000,0xbd353d35,0x3d80,0x3d353d35,0xbd6d3cc4,0xbcc43d6d,0x3cc43d6d,0x3d6d3cc4,
0x3cc4bd6d,0xbd6d3cc4,0x3d6d3cc4,0xbcc4bd6d,0x3d800000,0xbd35bd35,0x3d80,0x3d35bd35,0xbcc43d6d,0x3d6dbcc4,0xbd6dbcc4,0x3cc43d6d,0xbd800000,0x3d353d35,0xbd80,0xbd353d35,
0x3cc4bd6d,0xbd6d3cc4,0x3d6d3cc4,0xbcc4bd6d,0x3d800000,0xbd35bd35,0x3d80,0x3d35bd35,0xbcc43d6d,0x3d6dbcc4,0xbd6dbcc4,0x3cc43d6d,0xbd800000,0x3d353d35,0xbd80,0xbd353d35,
0xbd80,0xbd6dbcc4,0xbd353d35,0x3cc43d6d,0xbd0ebd55,0xbd7b3c48,0xbc483d7b,0x3d553d0e,0xbd800000,0xbcc43d6d,0x3d353d35,0x3d6dbcc4,0xbd553d0e,0x3c483d7b,0x3d7b3c48,0x3d0ebd55,
0x3d80,0x3d6d3cc4,0x3d35bd35,0xbcc4bd6d,0x3d0e3d55,0x3d7bbc48,0x3c48bd7b,0xbd55bd0e,0x3d800000,0x3cc4bd6d,0xbd35bd35,0xbd6d3cc4,0x3d55bd0e,0xbc48bd7b,0xbd7bbc48,0xbd0e3d55,
0xbd7bbc48,0x3d553d0e,0xbd0ebd55,0x3c483d7b,0xbd80,0xbcc43d6d,0x3d35bd35,0xbd6d3cc4,0xbc483d7b,0x3d0ebd55,0xbd553d0e,0x3d7bbc48,0xbd800000,0x3d6d3cc4,0xbd35bd35,0x3cc43d6d,
0x3d7b3c48,0xbd55bd0e,0x3d0e3d55,0xbc48bd7b,0x3d80,0x3cc4bd6d,0xbd353d35,0x3d6dbcc4,0x3c48bd7b,0xbd0e3d55,0x3d55bd0e,0xbd7b3c48,0x3d800000,0xbd6dbcc4,0x3d353d35,0xbcc4bd6d,
0x80003d80,0x8000bd80,0x80003d80,0x8000bd80,0x3d800000,0xbd800000,0x3d800000,0xbd800000,0x80003d80,0x8000bd80,0x80003d80,0x8000bd80,0x3d800000,0xbd800000,0x3d800000,0xbd800000,
0x80003d80,0x8000bd80,0x80003d80,0x8000bd80,0x3d800000,0xbd800000,0x3d800000,0xbd800000,0x80003d80,0x8000bd80,0x80003d80,0x8000bd80,0x3d800000,0xbd800000,0x3d800000,0xbd800000,
0x3d35bd35,0x3d353d35,0xbd353d35,0xbd35bd35,0x80003d80,0xbd800000,0x8000bd80,0x3d800000,0x3d35bd35,0x3d353d35,0xbd353d35,0xbd35bd35,0x80003d80,0xbd800000,0x8000bd80,0x3d800000,
0x3d35bd35,0x3d353d35,0xbd353d35,0xbd35bd35,0x80003d80,0xbd800000,0x8000bd80,0x3d800000,0x3d35bd35,0x3d353d35,0xbd353d35,0xbd35bd35,0x80003d80,0xbd800000,0x8000bd80,0x3d800000,
0x3d800000,0xbd6d3cc4,0x3d35bd35,0xbcc43d6d,0xbc48bd7b,0x3d0e3d55,0xbd55bd0e,0x3d7b3c48,0x80003d80,0xbcc4bd6d,0x3d353d35,0xbd6dbcc4,0x3d7bbc48,0xbd553d0e,0x3d0ebd55,0xbc483d7b,
0xbd800000,0x3d6dbcc4,0xbd353d35,0x3cc4bd6d,0x3c483d7b,0xbd0ebd55,0x3d553d0e,0xbd7bbc48,0x8000bd80,0x3cc43d6d,0xbd35bd35,0x3d6d3cc4,0xbd7b3c48,0x3d55bd0e,0xbd0e3d55,0x3c48bd7b,
0xbd55bd0e,0x3c48bd7b,0x3d7bbc48,0x3d0e3d55,0x3d800000,0x3cc43d6d,0xbd353d35,0xbd6dbcc4,0x3d0ebd55,0x3d7b3c48,0x3c483d7b,0xbd553d0e,0x80003d80,0xbd6d3cc4,0xbd35bd35,0x3cc4bd6d,
0x3d553d0e,0xbc483d7b,0xbd7b3c48,0xbd0ebd55,0xbd800000,0xbcc4bd6d,0x3d35bd35,0x3d6d3cc4,0xbd0e3d55,0xbd7bbc48,0xbc48bd7b,0x3d55bd0e,0x8000bd80,0x3d6dbcc4,0x3d353d35,0xbcc43d6d,
0x80003d80,0xbd35bd35,0x3d800000,0xbd353d35,0x3d6dbcc4,0xbcc43d6d,0xbcc4bd6d,0x3d6d3cc4,0x8000bd80,0x3d353d35,0xbd800000,0x3d35bd35,0xbd6d3cc4,0x3cc4bd6d,0x3cc43d6d,0xbd6dbcc4,
0x80003d80,0xbd35bd35,0x3d800000,0xbd353d35,0x3d6dbcc4,0xbcc43d6d,0xbcc4bd6d,0x3d6d3cc4,0x8000bd80,0x3d353d35,0xbd800000,0x3d35bd35,0xbd6d3cc4,0x3cc4bd6d,0x3cc43d6d,0xbd6dbcc4,
0x3cc4bd6d,0x3d6dbcc4,0x3d6d3cc4,0x3cc43d6d,0x80003d80,0xbd353d35,0xbd800000,0xbd35bd35,0xbcc43d6d,0xbd6d3cc4,0xbd6dbcc4,0xbcc4bd6d,0x8000bd80,0x3d35bd35,0x3d800000,0x3d353d35,
0x3cc4bd6d,0x3d6dbcc4,0x3d6d3cc4,0x3cc43d6d,0x80003d80,0xbd353d35,0xbd800000,0xbd35bd35,0xbcc43d6d,0xbd6d3cc4,0xbd6dbcc4,0xbcc4bd6d,0x8000bd80,0x3d35bd35,0x3d800000,0x3d353d35,
0x3d800000,0xbcc43d6d,0xbd35bd35,0x3d6dbcc4,0xbd0ebd55,0x3d7bbc48,0xbc483d7b,0xbd55bd0e,0x8000bd80,0x3d6d3cc4,0xbd353d35,0xbcc4bd6d,0xbd553d0e,0xbc48bd7b,0x3d7b3c48,0xbd0e3d55,
0xbd800000,0x3cc4bd6d,0x3d353d35,0xbd6d3cc4,0x3d0e3d55,0xbd7b3c48,0x3c48bd7b,0x3d553d0e,0x80003d80,0xbd6dbcc4,0x3d35bd35,0x3cc43d6d,0x3d55bd0e,0x3c483d7b,0xbd7bbc48,0x3d0ebd55,
0xbd7bbc48,0xbd55bd0e,0xbd0ebd55,0xbc48bd7b,0x3d800000,0x3d6d3cc4,0x3d353d35,0x3cc43d6d,0xbc483d7b,0xbd0e3d55,0xbd553d0e,0xbd7b3c48,0x8000bd80,0x3cc4bd6d,0x3d35bd35,0x3d6dbcc4,
0x3d7b3c48,0x3d553d0e,0x3d0e3d55,0x3c483d7b,0xbd800000,0xbd6dbcc4,0xbd35bd35,0xbcc4bd6d,0x3c48bd7b,0x3d0ebd55,0x3d55bd0e,0x3d7bbc48,0x80003d80,0xbcc43d6d,0xbd353d35,0xbd6d3cc4,
0x3d800000,0xbd800000,0x3d800000,0xbd800000,0xbd80,0x3d80,0xbd80,0x3d80,0x3d800000,0xbd800000,0x3d800000,0xbd800000,0xbd80,0x3d80,0xbd80,0x3d80,
0x3d800000,0xbd800000,0x3d800000,0xbd800000,0xbd80,0x3d80,0xbd80,0x3d80,0x3d800000,0xbd800000,0x3d800000,0xbd800000,0xbd80,0x3d80,0xbd80,0x3d80,
0xbd35bd35,0x3d35bd35,0x3d353d35,0xbd353d35,0x3d800000,0x3d80,0xbd800000,0xbd80,0xbd35bd35,0x3d35bd35,0x3d353d35,0xbd353d35,0x3d800000,0x3d80,0xbd800000,0xbd80,
0xbd35bd35,0x3d35bd35,0x3d353d35,0xbd353d35,0x3d800000,0x3d80,0xbd800000,0xbd80,0xbd35bd35,0x3d35bd35,0x3d353d35,0xbd353d35,0x3d800000,0x3d80,0xbd800000,0xbd80,
0xbd80,0x3cc43d6d,0xbd35bd35,0x3d6d3cc4,0xbd7b3c48,0x3d55bd0e,0xbd0e3d55,0x3c48bd7b,0x3d800000,0xbd6d3cc4,0x3d35bd35,0xbcc43d6d,0xbc48bd7b,0x3d0e3d55,0xbd55bd0e,0x3d7b3c48,
0x3d80,0xbcc4bd6d,0x3d353d35,0xbd6dbcc4,0x3d7bbc48,0xbd553d0e,0x3d0ebd55,0xbc483d7b,0xbd800000,0x3d6dbcc4,0xbd353d35,0x3cc4bd6d,0x3c483d7b,0xbd0ebd55,0x3d553d0e,0xbd7bbc48,
0xbd0e3d55,0xbd7bbc48,0xbc48bd7b,0x3d55bd0e,0xbd80,0x3d6dbcc4,0x3d353d35,0xbcc43d6d,0xbd55bd0e,0x3c48bd7b,0x3d7bbc48,0x3d0e3d55,0x3d800000,0x3cc43d6d,0xbd353d35,0xbd6dbcc4,
0x3d0ebd55,0x3d7b3c48,0x3c483d7b,0xbd553d0e,0x3d80,0xbd6d3cc4,0xbd35bd35,0x3cc4bd6d,0x3d553d0e,0xbc483d7b,0xbd7b3c48,0xbd0ebd55,0xbd800000,0xbcc4bd6d,0x3d35bd35,0x3d6d3cc4,
0x3d800000,0xbd353d35,0xbd80,0x3d353d35,0xbcc4bd6d,0x3d6d3cc4,0xbd6d3cc4,0x3cc4bd6d,0xbd800000,0x3d35bd35,0x3d80,0xbd35bd35,0x3cc43d6d,0xbd6dbcc4,0x3d6dbcc4,0xbcc43d6d,
0x3d800000,0xbd353d35,0xbd80,0x3d353d35,0xbcc4bd6d,0x3d6d3cc4,0xbd6d3cc4,0x3cc4bd6d,0xbd800000,0x3d35bd35,0x3d80,0xbd35bd35,0x3cc43d6d,0xbd6dbcc4,0x3d6dbcc4,0xbcc43d6d,
0xbd6dbcc4,0xbcc4bd6d,0x3cc4bd6d,0x3d6dbcc4,0x3d800000,0x3d353d35,0x3d80,0xbd353d35,0x3d6d3cc4,0x3cc43d6d,0xbcc43d6d,0xbd6d3cc4,0xbd800000,0xbd35bd35,0xbd80,0x3d35bd35,
0xbd6dbcc4,0xbcc4bd6d,0x3cc4bd6d,0x3d6dbcc4,0x3d800000,0x3d353d35,0x3d80,0xbd353d35,0x3d6d3cc4,0x3cc43d6d,0xbcc43d6d,0xbd6d3cc4,0xbd800000,0xbd35bd35,0xbd80,0x3d35bd35,
0xbd80,0x3d6d3cc4,0xbd353d35,0xbcc4bd6d,0xbd553d0e,0xbc48bd7b,0x3d7b3c48,0xbd0e3d55,0xbd800000,0x3cc4bd6d,0x3d353d35,0xbd6d3cc4,0x3d0e3d55,0xbd7b3c48,0x3c48bd7b,0x3d553d0e,
0x3d80,0xbd6dbcc4,0x3d35bd35,0x3cc43d6d,0x3d55bd0e,0x3c483d7b,0xbd7bbc48,0x3d0ebd55,0x3d800000,0xbcc43d6d,0xbd35bd35,0x3d6dbcc4,0xbd0ebd55,0x3d7bbc48,0xbc483d7b,0xbd55bd0e,
0xbc483d7b,0xbd0e3d55,0xbd553d0e,0xbd7b3c48,0xbd80,0x3cc4bd6d,0x3d35bd35,0x3d6dbcc4,0x3d7b3c48,0x3d553d0e,0x3d0e3d55,0x3c483d7b,0xbd800000,0xbd6dbcc4,0xbd35bd35,0xbcc4bd6d,
0x3c48bd7b,0x3d0ebd55,0x3d55bd0e,0x3d7bbc48,0x3d80,0xbcc43d6d,0xbd353d35,0xbd6d3cc4,0xbd7bbc48,0xbd55bd0e,0xbd0ebd55,0xbc48bd7b,0x3d800000,0x3d6d3cc4,0x3d353d35,0x3cc43d6d,
0x80003d80,0x80003d80,0x80003d80,0x80003d80,0x8000bd80,0x8000bd80,0x8000bd80,0x8000bd80,0x80003d80,0x80003d80,0x80003d80,0x80003d80,0x8000bd80,0x8000bd80,0x8000bd80,0x8000bd80,
0x80003d80,0x80003d80,0x80003d80,0x80003d80,0x8000bd80,0x8000bd80,0x8000bd80,0x8000bd80,0x80003d80,0x80003d80,0x80003d80,0x80003d80,0x8000bd80,0x8000bd80,0x8000bd80,0x8000bd80,
0xbd35bd35,0xbd353d35,0x3d353d35,0x3d35bd35,0x80003d80,0x3d800000,0x8000bd80,0xbd800000,0xbd35bd35,0xbd353d35,0x3d353d35,0x3d35bd35,0x80003d80,0x3d800000,0x8000bd80,0xbd800000,
0xbd35bd35,0xbd353d35,0x3d353d35,0x3d35bd35,0x80003d80,0x3d800000,0x8000bd80,0xbd800000,0xbd35bd35,0xbd353d35,0x3d353d35,0x3d35bd35,0x80003d80,0x3d800000,0x8000bd80,0xbd800000,
0x3d800000,0x3d6dbcc4,0x3d35bd35,0x3cc4bd6d,0xbd7b3c48,0xbd553d0e,0xbd0e3d55,0xbc483d7b,0x80003d80,0x3cc43d6d,0x3d353d35,0x3d6d3cc4,0xbc48bd7b,0xbd0ebd55,0xbd55bd0e,0xbd7bbc48,
0xbd800000,0xbd6d3cc4,0xbd353d35,0xbcc43d6d,0x3d7bbc48,0x3d55bd0e,0x3d0ebd55,0x3c48bd7b,0x8000bd80,0xbcc4bd6d,0xbd35bd35,0xbd6dbcc4,0x3c483d7b,0x3d0e3d55,0x3d553d0e,0x3d7b3c48,
0xbd0e3d55,0x3d7b3c48,0xbc48bd7b,0xbd553d0e,0x3d800000,0xbcc4bd6d,0xbd353d35,0x3d6d3cc4,0xbd55bd0e,0xbc483d7b,0x3d7bbc48,0xbd0ebd55,0x80003d80,0x3d6dbcc4,0xbd35bd35,0xbcc43d6d,
0x3d0ebd55,0xbd7bbc48,0x3c483d7b,0x3d55bd0e,0xbd800000,0x3cc43d6d,0x3d35bd35,0xbd6dbcc4,0x3d553d0e,0x3c48bd7b,0xbd7b3c48,0x3d0e3d55,0x8000bd80,0xbd6d3cc4,0x3d353d35,0x3cc4bd6d,
0x80003d80,0x3d353d35,0x3d800000,0x3d35bd35,0xbcc4bd6d,0xbd6dbcc4,0xbd6d3cc4,0xbcc43d6d,0x8000bd80,0xbd35bd35,0xbd800000,0xbd353d35,0x3cc43d6d,0x3d6d3cc4,0x3d6dbcc4,0x3cc4bd6d,
0x80003d80,0x3d353d35,0x3d800000,0x3d35bd35,0xbcc4bd6d,0xbd6dbcc4,0xbd6d3cc4,0xbcc43d6d,0x8000bd80,0xbd35bd35,0xbd800000,0xbd353d35,0x3cc43d6d,0x3d6d3cc4,0x3d6dbcc4,0x3cc4bd6d,
0xbd6dbcc4,0x3cc43d6d,0x3cc4bd6d,0xbd6d3cc4,0x80003d80,0x3d35bd35,0xbd800000,0x3d353d35,0x3d6d3cc4,0xbcc4bd6d,0xbcc43d6d,0x3d6dbcc4,0x8000bd80,0xbd353d35,0x3d800000,0xbd35bd35,
0xbd6dbcc4,0x3cc43d6d,0x3cc4bd6d,0xbd6d3cc4,0x80003d80,0x3d35bd35,0xbd800000,0x3d353d35,0x3d6d3cc4,0xbcc4bd6d,0xbcc43d6d,0x3d6dbcc4,0x8000bd80,0xbd353d35,0x3d800000,0xbd35bd35,
0x3d800000,0x3cc4bd6d,0xbd35bd35,0xbd6d3cc4,0xbd553d0e,0x3c483d7b,0x3d7b3c48,0x3d0ebd55,0x8000bd80,0xbd6dbcc4,0xbd353d35,0x3cc43d6d,0x3d0e3d55,0x3d7bbc48,0x3c48bd7b,0xbd55bd0e,
0xbd800000,0xbcc43d6d,0x3d353d35,0x3d6dbcc4,0x3d55bd0e,0xbc48bd7b,0xbd7bbc48,0xbd0e3d55,0x80003d80,0x3d6d3cc4,0x3d35bd35,0xbcc4bd6d,0xbd0ebd55,0xbd7b3c48,0xbc483d7b,0x3d553d0e,
0xbc483d7b,0x3d0ebd55,0xbd553d0e,0x3d7bbc48,0x3d800000,0xbd6dbcc4,0x3d353d35,0xbcc4bd6d,0x3d7b3c48,0xbd55bd0e,0x3d0e3d55,0xbc48bd7b,0x8000bd80,0xbcc43d6d,0x3d35bd35,0xbd6d3cc4,
0x3c48bd7b,0xbd0e3d55,0x3d55bd0e,0xbd7b3c48,0xbd800000,0x3d6d3cc4,0xbd35bd35,0x3cc43d6d,0xbd7bbc48,0x3d553d0e,0xbd0ebd55,0x3c483d7b,0x80003d80,0x3cc4bd6d,0xbd353d35,0x3d6dbcc4,
0x3d800000,0x3d800000,0x3d800000,0x3d800000,0xbd800000,0xbd800000,0xbd800000,0xbd800000,0x3d800000,0x3d800000,0x3d800000,0x3d800000,0xbd800000,0xbd800000,0xbd800000,0xbd800000,
0x3d800000,0x3d800000,0x3d800000,0x3d800000,0xbd800000,0xbd800000,0xbd800000,0xbd800000,0x3d800000,0x3d800000,0x3d800000,0x3d800000,0xbd800000,0xbd800000,0xbd800000,0xbd800000,
0xbd353d35,0x3d353d35,0x3d35bd35,0xbd35bd35,0x3d800000,0xbd80,0xbd800000,0x3d80,0xbd353d35,0x3d353d35,0x3d35bd35,0xbd35bd35,0x3d800000,0xbd80,0xbd800000,0x3d80,
0xbd353d35,0x3d353d35,0x3d35bd35,0xbd35bd35,0x3d800000,0xbd80,0xbd800000,0x3d80,0xbd353d35,0x3d353d35,0x3d35bd35,0xbd35bd35,0x3d800000,0xbd80,0xbd800000,0x3d80,
0xbd80,0xbcc4bd6d,0xbd35bd35,0xbd6dbcc4,0x3c483d7b,0x3d0e3d55,0x3d553d0e,0x3d7b3c48,0x3d800000,0x3d6dbcc4,0x3d35bd35,0x3cc4bd6d,0xbd7b3c48,0xbd553d0e,0xbd0e3d55,0xbc483d7b,
0x3d80,0x3cc43d6d,0x3d353d35,0x3d6d3cc4,0xbc48bd7b,0xbd0ebd55,0xbd55bd0e,0xbd7bbc48,0xbd800000,0xbd6d3cc4,0xbd353d35,0xbcc43d6d,0x3d7bbc48,0x3d55bd0e,0x3d0ebd55,0x3c48bd7b,
0x3d553d0e,0x3c48bd7b,0xbd7b3c48,0x3d0e3d55,0xbd80,0xbd6d3cc4,0x3d353d35,0x3cc4bd6d,0xbd0e3d55,0x3d7b3c48,0xbc48bd7b,0xbd553d0e,0x3d800000,0xbcc4bd6d,0xbd353d35,0x3d6d3cc4,
0xbd55bd0e,0xbc483d7b,0x3d7bbc48,0xbd0ebd55,0x3d80,0x3d6dbcc4,0xbd35bd35,0xbcc43d6d,0x3d0ebd55,0xbd7bbc48,0x3c483d7b,0x3d55bd0e,0xbd800000,0x3cc43d6d,0x3d35bd35,0xbd6dbcc4,
0x3d800000,0x3d35bd35,0xbd80,0xbd35bd35,0xbd6d3cc4,0xbcc43d6d,0x3cc43d6d,0x3d6d3cc4,0xbd800000,0xbd353d35,0x3d80,0x3d353d35,0x3d6dbcc4,0x3cc4bd6d,0xbcc4bd6d,0xbd6dbcc4,
0x3d800000,0x3d35bd35,0xbd80,0xbd35bd35,0xbd6d3cc4,0xbcc43d6d,0x3cc43d6d,0x3d6d3cc4,0xbd800000,0xbd353d35,0x3d80,0x3d353d35,0x3d6dbcc4,0x3cc4bd6d,0xbcc4bd6d,0xbd6dbcc4,
0xbcc43d6d,0x3d6dbcc4,0xbd6dbcc4,0x3cc43d6d,0x3d800000,0xbd35bd35,0x3d80,0x3d35bd35,0x3cc4bd6d,0xbd6d3cc4,0x3d6d3cc4,0xbcc4bd6d,0xbd800000,0x3d353d35,0xbd80,0xbd353d35,
0xbcc43d6d,0x3d6dbcc4,0xbd6dbcc4,0x3cc43d6d,0x3d800000,0xbd35bd35,0x3d80,0x3d35bd35,0x3cc4bd6d,0xbd6d3cc4,0x3d6d3cc4,0xbcc4bd6d,0xbd800000,0x3d353d35,0xbd80,0xbd353d35,
0xbd80,0xbd6dbcc4,0xbd353d35,0x3cc43d6d,0x3d0e3d55,0x3d7bbc48,0x3c48bd7b,0xbd55bd0e,0xbd800000,0xbcc43d6d,0x3d353d35,0x3d6dbcc4,0x3d55bd0e,0xbc48bd7b,0xbd7bbc48,0xbd0e3d55,
0x3d80,0x3d6d3cc4,0x3d35bd35,0xbcc4bd6d,0xbd0ebd55,0xbd7b3c48,0xbc483d7b,0x3d553d0e,0x3d800000,0x3cc4bd6d,0xbd35bd35,0xbd6d3cc4,0xbd553d0e,0x3c483d7b,0x3d7b3c48,0x3d0ebd55,
0x3d7b3c48,0xbd55bd0e,0x3d0e3d55,0xbc48bd7b,0xbd80,0xbcc43d6d,0x3d35bd35,0xbd6d3cc4,0x3c48bd7b,0xbd0e3d55,0x3d55bd0e,0xbd7b3c48,0xbd800000,0x3d6d3cc4,0xbd35bd35,0x3cc43d6d,
0xbd7bbc48,0x3d553d0e,0xbd0ebd55,0x3c483d7b,0x3d80,0x3cc4bd6d,0xbd353d35,0x3d6dbcc4,0xbc483d7b,0x3d0ebd55,0xbd553d0e,0x3d7bbc48,0x3d800000,0xbd6dbcc4,0x3d353d35,0xbcc4bd6d,
0x80003d80,0x8000bd80,0x80003d80,0x8000bd80,0xbd800000,0x3d800000,0xbd800000,0x3d800000,0x80003d80,0x8000bd80,0x80003d80,0x8000bd80,0xbd800000,0x3d800000,0xbd800000,0x3d800000,
0x80003d80,0x8000bd80,0x80003d80,0x8000bd80,0xbd800000,0x3d800000,0xbd800000,0x3d800000,0x80003d80,0x8000bd80,0x80003d80,0x8000bd80,0xbd800000,0x3d800000,0xbd800000,0x3d800000,
0xbd353d35,0xbd35bd35,0x3d35bd35,0x3d353d35,0x80003d80,0xbd800000,0x8000bd80,0x3d800000,0xbd353d35,0xbd35bd35,0x3d35bd35,0x3d353d35,0x80003d80,0xbd800000,0x8000bd80,0x3d800000,
0xbd353d35,0xbd35bd35,0x3d35bd35,0x3d353d35,0x80003d80,0xbd800000,0x8000bd80,0x3d800000,0xbd353d35,0xbd35bd35,0x3d35bd35,0x3d353d35,0x80003d80,0xbd800000,0x8000bd80,0x3d800000,
0x3d800000,0xbd6d3cc4,0x3d35bd35,0xbcc43d6d,0x3c483d7b,0xbd0ebd55,0x3d553d0e,0xbd7bbc48,0x80003d80,0xbcc4bd6d,0x3d353d35,0xbd6dbcc4,0xbd7b3c48,0x3d55bd0e,0xbd0e3d55,0x3c48bd7b,
0xbd800000,0x3d6dbcc4,0xbd353d35,0x3cc4bd6d,0xbc48bd7b,0x3d0e3d55,0xbd55bd0e,0x3d7b3c48,0x8000bd80,0x3cc43d6d,0xbd35bd35,0x3d6d3cc4,0x3d7bbc48,0xbd553d0e,0x3d0ebd55,0xbc483d7b,
0x3d553d0e,0xbc483d7b,0xbd7b3c48,0xbd0ebd55,0x3d800000,0x3cc43d6d,0xbd353d35,0xbd6dbcc4,0xbd0e3d55,0xbd7bbc48,0xbc48bd7b,0x3d55bd0e,0x80003d80,0xbd6d3cc4,0xbd35bd35,0x3cc4bd6d,
0xbd55bd0e,0x3c48bd7b,0x3d7bbc48,0x3d0e3d55,0xbd800000,0xbcc4bd6d,0x3d35bd35,0x3d6d3cc4,0x3d0ebd55,0x3d7b3c48,0x3c483d7b,0xbd553d0e,0x8000bd80,0x3d6dbcc4,0x3d353d35,0xbcc43d6d,
0x80003d80,0xbd35bd35,0x3d800000,0xbd353d35,0xbd6d3cc4,0x3cc4bd6d,0x3cc43d6d,0xbd6dbcc4,0x8000bd80,0x3d353d35,0xbd800000,0x3d35bd35,0x3d6dbcc4,0xbcc43d6d,0xbcc4bd6d,0x3d6d3cc4,
0x80003d80,0xbd35bd35,0x3d800000,0xbd353d35,0xbd6d3cc4,0x3cc4bd6d,0x3cc43d6d,0xbd6dbcc4,0x8000bd80,0x3d353d35,0xbd800000,0x3d35bd35,0x3d6dbcc4,0xbcc43d6d,0xbcc4bd6d,0x3d6d3cc4,
0xbcc43d6d,0xbd6d3cc4,0xbd6dbcc4,0xbcc4bd6d,0x80003d80,0xbd353d35,0xbd800000,0xbd35bd35,0x3cc4bd6d,0x3d6dbcc4,0x3d6d3cc4,0x3cc43d6d,0x8000bd80,0x3d35bd35,0x3d800000,0x3d353d35,
0xbcc43d6d,0xbd6d3cc4,0xbd6dbcc4,0xbcc4bd6d,0x80003d80,0xbd353d35,0xbd800000,0xbd35bd35,0x3cc4bd6d,0x3d6dbcc4,0x3d6d3cc4,0x3cc43d6d,0x8000bd80,0x3d35bd35,0x3d800000,0x3d353d35,
0x3d800000,0xbcc43d6d,0xbd35bd35,0x3d6dbcc4,0x3d0e3d55,0xbd7b3c48,0x3c48bd7b,0x3d553d0e,0x8000bd80,0x3d6d3cc4,0xbd353d35,0xbcc4bd6d,0x3d55bd0e,0x3c483d7b,0xbd7bbc48,0x3d0ebd55,
0xbd800000,0x3cc4bd6d,0x3d353d35,0xbd6d3cc4,0xbd0ebd55,0x3d7bbc48,0xbc483d7b,0xbd55bd0e,0x80003d80,0xbd6dbcc4,0x3d35bd35,0x3cc43d6d,0xbd553d0e,0xbc48bd7b,0x3d7b3c48,0xbd0e3d55,
0x3d7b3c48,0x3d553d0e,0x3d0e3d55,0x3c483d7b,0x3d800000,0x3d6d3cc4,0x3d353d35,0x3cc43d6d,0x3c48bd7b,0x3d0ebd55,0x3d55bd0e,0x3d7bbc48,0x8000bd80,0x3cc4bd6d,0x3d35bd35,0x3d6dbcc4,
0xbd7bbc48,0xbd55bd0e,0xbd0ebd55,0xbc48bd7b,0xbd800000,0xbd6dbcc4,0xbd35bd35,0xbcc4bd6d,0xbc483d7b,0xbd0e3d55,0xbd553d0e,0xbd7b3c48,0x80003d80,0xbcc43d6d,0xbd353d35,0xbd6d3cc4,
0x3d800000,0xbd800000,0x3d800000,0xbd800000,0x3d80,0xbd80,0x3d80,0xbd80,0x3d800000,0xbd800000,0x3d800000,0xbd800000,0x3d80,0xbd80,0x3d80,0xbd80,
0x3d800000,0xbd800000,0x3d800000,0xbd800000,0x3d80,0xbd80,0x3d80,0xbd80,0x3d800000,0xbd800000,0x3d800000,0xbd800000,0x3d80,0xbd80,0x3d80,0xbd80,
0x3d353d35,0xbd353d35,0xbd35bd35,0x3d35bd35,0x3d800000,0x3d80,0xbd800000,0xbd80,0x3d353d35,0xbd353d35,0xbd35bd35,0x3d35bd35,0x3d800000,0x3d80,0xbd800000,0xbd80,
0x3d353d35,0xbd353d35,0xbd35bd35,0x3d35bd35,0x3d800000,0x3d80,0xbd800000,0xbd80,0x3d353d35,0xbd353d35,0xbd35bd35,0x3d35bd35,0x3d800000,0x3d80,0xbd800000,0xbd80,
0xbd80,0x3cc43d6d,0xbd35bd35,0x3d6d3cc4,0x3d7bbc48,0xbd553d0e,0x3d0ebd55,0xbc483d7b,0x3d800000,0xbd6d3cc4,0x3d35bd35,0xbcc43d6d,0x3c483d7b,0xbd0ebd55,0x3d553d0e,0xbd7bbc48,
0x3d80,0xbcc4bd6d,0x3d353d35,0xbd6dbcc4,0xbd7b3c48,0x3d55bd0e,0xbd0e3d55,0x3c48bd7b,0xbd800000,0x3d6dbcc4,0xbd353d35,0x3cc4bd6d,0xbc48bd7b,0x3d0e3d55,0xbd55bd0e,0x3d7b3c48,
0x3d0ebd55,0x3d7b3c48,0x3c483d7b,0xbd553d0e,0xbd80,0x3d6dbcc4,0x3d353d35,0xbcc43d6d,0x3d553d0e,0xbc483d7b,0xbd7b3c48,0xbd0ebd55,0x3d800000,0x3cc43d6d,0xbd353d35,0xbd6dbcc4,
0xbd0e3d55,0xbd7bbc48,0xbc48bd7b,0x3d55bd0e,0x3d80,0xbd6d3cc4,0xbd35bd35,0x3cc4bd6d,0xbd55bd0e,0x3c48bd7b,0x3d7bbc48,0x3d0e3d55,0xbd800000,0xbcc4bd6d,0x3d35bd35,0x3d6d3cc4,
0x3d800000,0xbd353d35,0xbd80,0x3d353d35,0x3cc43d6d,0xbd6dbcc4,0x3d6dbcc4,0xbcc43d6d,0xbd800000,0x3d35bd35,0x3d80,0xbd35bd35,0xbcc4bd6d,0x3d6d3cc4,0xbd6d3cc4,0x3cc4bd6d,
0x3d800000,0xbd353d35,0xbd80,0x3d353d35,0x3cc43d6d,0xbd6dbcc4,0x3d6dbcc4,0xbcc43d6d,0xbd800000,0x3d35bd35,0x3d80,0xbd35bd35,0xbcc4bd6d,0x3d6d3cc4,0xbd6d3cc4,0x3cc4bd6d,
0x3d6d3cc4,0x3cc43d6d,0xbcc43d6d,0xbd6d3cc4,0x3d800000,0x3d353d35,0x3d80,0xbd353d35,0xbd6dbcc4,0xbcc4bd6d,0x3cc4bd6d,0x3d6dbcc4,0xbd800000,0xbd35bd35,0xbd80,0x3d35bd35,
0x3d6d3cc4,0x3cc43d6d,0xbcc43d6d,0xbd6d3cc4,0x3d800000,0x3d353d35,0x3d80,0xbd353d35,0xbd6dbcc4,0xbcc4bd6d,0x3cc4bd6d,0x3d6dbcc4,0xbd800000,0xbd35bd35,0xbd80,0x3d35bd35,
0xbd80,0x3d6d3cc4,0xbd353d35,0xbcc4bd6d,0x3d55bd0e,0x3c483d7b,0xbd7bbc48,0x3d0ebd55,0xbd800000,0x3cc4bd6d,0x3d353d35,0xbd6d3cc4,0xbd0ebd55,0x3d7bbc48,0xbc483d7b,0xbd55bd0e,
0x3d80,0xbd6dbcc4,0x3d35bd35,0x3cc43d6d,0xbd553d0e,0xbc48bd7b,0x3d7b3c48,0xbd0e3d55,0x3d800000,0xbcc43d6d,0xbd35bd35,0x3d6dbcc4,0x3d0e3d55,0xbd7b3c48,0x3c48bd7b,0x3d553d0e,
0x3c48bd7b,0x3d0ebd55,0x3d55bd0e,0x3d7bbc48,0xbd80,0x3cc4bd6d,0x3d35bd35,0x3d6dbcc4,0xbd7bbc48,0xbd55bd0e,0xbd0ebd55,0xbc48bd7b,0xbd800000,0xbd6dbcc4,0xbd35bd35,0xbcc4bd6d,
0xbc483d7b,0xbd0e3d55,0xbd553d0e,0xbd7b3c48,0x3d80,0xbcc43d6d,0xbd353d35,0xbd6d3cc4,0x3d7b3c48,0x3d553d0e,0x3d0e3d55,0x3c483d7b,0x3d800000,0x3d6d3cc4,0x3d353d35,0x3cc43d6d,
0x3d80,0x3d80,0x3d80,0x3d80,0x3d80,0x3d80,0x3d80,0x3d80,0x3d80,0x3d80,0x3d80,0x3d80,0x3d80,0x3d80,0x3d80,0x3d80,
0x3d80,0x3d80,0x3d80,0x3d80,0x3d80,0x3d80,0x3d80,0x3d80,0x3d80,0x3d80,0x3d80,0x3d80,0x3d80,0x3d80,0x3d80,0x3d80,
0xbd353d35,0xbd553d0e,0xbd6d3cc4,0xbd7b3c48,0x3d80,0xbc483d7b,0xbcc43d6d,0xbd0e3d55,0xbd35bd35,0xbd0ebd55,0xbcc4bd6d,0xbc48bd7b,0xbd800000,0xbd7bbc48,0xbd6dbcc4,0xbd55bd0e,
0x3d35bd35,0x3d55bd0e,0x3d6dbcc4,0x3d7bbc48,0xbd80,0x3c48bd7b,0x3cc4bd6d,0x3d0ebd55,0x3d353d35,0x3d0e3d55,0x3cc43d6d,0x3c483d7b,0x3d800000,0x3d7b3c48,0x3d6d3cc4,0x3d553d0e,
0xbd80,0x3cc4bd6d,0x3d35bd35,0x3d6dbcc4,0x3d800000,0x3d6d3cc4,0x3d353d35,0x3cc43d6d,0x3d80,0xbcc43d6d,0xbd353d35,0xbd6d3cc4,0xbd800000,0xbd6dbcc4,0xbd35bd35,0xbcc4bd6d,
0xbd80,0x3cc4bd6d,0x3d35bd35,0x3d6dbcc4,0x3d800000,0x3d6d3cc4,0x3d353d35,0x3cc43d6d,0x3d80,0xbcc43d6d,0xbd353d35,0xbd6d3cc4,0xbd800000,0xbd6dbcc4,0xbd35bd35,0xbcc4bd6d,
0xbd353d35,0xbd7b3c48,0xbd6dbcc4,0xbd0ebd55,0x3d800000,0x3d553d0e,0x3cc43d6d,0xbc483d7b,0xbd35bd35,0xbc48bd7b,0x3cc4bd6d,0x3d55bd0e,0x3d80,0xbd0e3d55,0xbd6d3cc4,0xbd7bbc48,
0x3d35bd35,0x3d7bbc48,0x3d6d3cc4,0x3d0e3d55,0xbd800000,0xbd55bd0e,0xbcc4bd6d,0x3c48bd7b,0x3d353d35,0x3c483d7b,0xbcc43d6d,0xbd553d0e,0xbd80,0x3d0ebd55,0x3d6dbcc4,0x3d7b3c48,
0x3d80,0xbd353d35,0xbd800000,0xbd35bd35,0xbd80,0x3d35bd35,0x3d800000,0x3d353d35,0x3d80,0xbd353d35,0xbd800000,0xbd35bd35,0xbd80,0x3d35bd35,0x3d800000,0x3d353d35,
0x3d80,0xbd353d35,0xbd800000,0xbd35bd35,0xbd80,0x3d35bd35,0x3d800000,0x3d353d35,0x3d80,0xbd353d35,0xbd800000,0xbd35bd35,0xbd80,0x3d35bd35,0x3d800000,0x3d353d35,
0xbd353d35,0xbd7bbc48,0xbcc4bd6d,0x3d0ebd55,0xbd80,0x3d55bd0e,0x3d6d3cc4,0x3c483d7b,0xbd35bd35,0x3c48bd7b,0x3d6dbcc4,0x3d553d0e,0x3d800000,0x3d0e3d55,0xbcc43d6d,0xbd7b3c48,
0x3d35bd35,0x3d7b3c48,0x3cc43d6d,0xbd0e3d55,0x3d80,0xbd553d0e,0xbd6dbcc4,0xbc48bd7b,0x3d353d35,0xbc483d7b,0xbd6d3cc4,0xbd55bd0e,0xbd800000,0xbd0ebd55,0x3cc4bd6d,0x3d7bbc48,
0xbd80,0x3d6dbcc4,0x3d353d35,0xbcc43d6d,0xbd800000,0xbcc4bd6d,0x3d35bd35,0x3d6d3cc4,0x3d80,0xbd6d3cc4,0xbd35bd35,0x3cc4bd6d,0x3d800000,0x3cc43d6d,0xbd353d35,0xbd6dbcc4,
0xbd80,0x3d6dbcc4,0x3d353d35,0xbcc43d6d,0xbd800000,0xbcc4bd6d,0x3d35bd35,0x3d6d3cc4,0x3d80,0xbd6d3cc4,0xbd35bd35,0x3cc4bd6d,0x3d800000,0x3cc43d6d,0xbd353d35,0xbd6dbcc4,
0xbd353d35,0xbd55bd0e,0x3cc4bd6d,0x3d7b3c48,0xbd800000,0xbc48bd7b,0x3d6dbcc4,0x3d0e3d55,0xbd35bd35,0x3d0ebd55,0x3d6d3cc4,0xbc483d7b,0xbd80,0x3d7bbc48,0x3cc43d6d,0xbd553d0e,
0x3d35bd35,0x3d553d0e,0xbcc43d6d,0xbd7bbc48,0x3d800000,0x3c483d7b,0xbd6d3cc4,0xbd0ebd55,0x3d353d35,0xbd0e3d55,0xbd6dbcc4,0x3c48bd7b,0x3d80,0xbd7b3c48,0xbcc4bd6d,0x3d55bd0e,
0xbd800000,0xbd800000,0xbd800000,0xbd800000,0xbd800000,0xbd800000,0xbd800000,0xbd800000,0xbd800000,0xbd800000,0xbd800000,0xbd800000,0xbd800000,0xbd800000,0xbd800000,0xbd800000,
0xbd800000,0xbd800000,0xbd800000,0xbd800000,0xbd800000,0xbd800000,0xbd800000,0xbd800000,0xbd800000,0xbd800000,0xbd800000,0xbd800000,0xbd800000,0xbd800000,0xbd800000,0xbd800000,
0xbd35bd35,0xbd0ebd55,0xbcc4bd6d,0xbc48bd7b,0xbd800000,0xbd7bbc48,0xbd6dbcc4,0xbd55bd0e,0x3d35bd35,0x3d55bd0e,0x3d6dbcc4,0x3d7bbc48,0x8000bd80,0x3c48bd7b,0x3cc4bd6d,0x3d0ebd55,
0x3d353d35,0x3d0e3d55,0x3cc43d6d,0x3c483d7b,0x3d800000,0x3d7b3c48,0x3d6d3cc4,0x3d553d0e,0xbd353d35,0xbd553d0e,0xbd6d3cc4,0xbd7b3c48,0x80003d80,0xbc483d7b,0xbcc43d6d,0xbd0e3d55,
0x3d800000,0x3d6d3cc4,0x3d353d35,0x3cc43d6d,0x80003d80,0xbcc43d6d,0xbd353d35,0xbd6d3cc4,0xbd800000,0xbd6dbcc4,0xbd35bd35,0xbcc4bd6d,0x8000bd80,0x3cc4bd6d,0x3d35bd35,0x3d6dbcc4,
0x3d800000,0x3d6d3cc4,0x3d353d35,0x3cc43d6d,0x80003d80,0xbcc43d6d,0xbd353d35,0xbd6d3cc4,0xbd800000,0xbd6dbcc4,0xbd35bd35,0xbcc4bd6d,0x8000bd80,0x3cc4bd6d,0x3d35bd35,0x3d6dbcc4,
0xbd35bd35,0xbc48bd7b,0x3cc4bd6d,0x3d55bd0e,0x80003d80,0xbd0e3d55,0xbd6d3cc4,0xbd7bbc48,0x3d35bd35,0x3d7bbc48,0x3d6d3cc4,0x3d0e3d55,0xbd800000,0xbd55bd0e,0xbcc4bd6d,0x3c48bd7b,
0x3d353d35,0x3c483d7b,0xbcc43d6d,0xbd553d0e,0x8000bd80,0x3d0ebd55,0x3d6dbcc4,0x3d7b3c48,0xbd353d35,0xbd7b3c48,0xbd6dbcc4,0xbd0ebd55,0x3d800000,0x3d553d0e,0x3cc43d6d,0xbc483d7b,
0xbd800000,0xbd35bd35,0x8000bd80,0x3d35bd35,0x3d800000,0x3d353d35,0x80003d80,0xbd353d35,0xbd800000,0xbd35bd35,0x8000bd80,0x3d35bd35,0x3d800000,0x3d353d35,0x80003d80,0xbd353d35,
0xbd800000,0xbd35bd35,0x8000bd80,0x3d35bd35,0x3d800000,0x3d353d35,0x80003d80,0xbd353d35,0xbd800000,0xbd35bd35,0x8000bd80,0x3d35bd35,0x3d800000,0x3d353d35,0x80003d80,0xbd353d35,
0xbd35bd35,0x3c48bd7b,0x3d6dbcc4,0x3d553d0e,0x3d800000,0x3d0e3d55,0xbcc43d6d,0xbd7b3c48,0x3d35bd35,0x3d7b3c48,0x3cc43d6d,0xbd0e3d55,0x80003d80,0xbd553d0e,0xbd6dbcc4,0xbc48bd7b,
0x3d353d35,0xbc483d7b,0xbd6d3cc4,0xbd55bd0e,0xbd800000,0xbd0ebd55,0x3cc4bd6d,0x3d7bbc48,0xbd353d35,0xbd7bbc48,0xbcc4bd6d,0x3d0ebd55,0x8000bd80,0x3d55bd0e,0x3d6d3cc4,0x3c483d7b,
0x3d800000,0x3cc43d6d,0xbd353d35,0xbd6dbcc4,0x8000bd80,0x3d6dbcc4,0x3d353d35,0xbcc43d6d,0xbd800000,0xbcc4bd6d,0x3d35bd35,0x3d6d3cc4,0x80003d80,0xbd6d3cc4,0xbd35bd35,0x3cc4bd6d,
0x3d800000,0x3cc43d6d,0xbd353d35,0xbd6dbcc4,0x8000bd80,0x3d6dbcc4,0x3d353d35,0xbcc43d6d,0xbd800000,0xbcc4bd6d,0x3d35bd35,0x3d6d3cc4,0x80003d80,0xbd6d3cc4,0xbd35bd35,0x3cc4bd6d,
0xbd35bd35,0x3d0ebd55,0x3d6d3cc4,0xbc483d7b,0x8000bd80,0x3d7bbc48,0x3cc43d6d,0xbd553d0e,0x3d35bd35,0x3d553d0e,0xbcc43d6d,0xbd7bbc48,0x3d800000,0x3c483d7b,0xbd6d3cc4,0xbd0ebd55,
0x3d353d35,0xbd0e3d55,0xbd6dbcc4,0x3c48bd7b,0x80003d80,0xbd7b3c48,0xbcc4bd6d,0x3d55bd0e,0xbd353d35,0xbd55bd0e,0x3cc4bd6d,0x3d7b3c48,0xbd800000,0xbc48bd7b,0x3d6dbcc4,0x3d0e3d55,
0x3d80,0xbd800000,0xbd80,0x3d800000,0x3d80,0xbd800000,0xbd80,0x3d800000,0x3d80,0xbd800000,0xbd80,0x3d800000,0x3d80,0xbd800000,0xbd80,0x3d800000,
0x3d80,0xbd800000,0xbd80,0x3d800000,0x3d80,0xbd800000,0xbd80,0x3d800000,0x3d80,0xbd800000,0xbd80,0x3d800000,0x3d80,0xbd800000,0xbd80,0x3d800000,
0xbd353d35,0xbd0ebd55,0x3d6dbcc4,0x3c483d7b,0x3d80,0xbd7bbc48,0x3cc4bd6d,0x3d553d0e,0xbd35bd35,0x3d55bd0e,0x3cc43d6d,0xbd7b3c48,0xbd800000,0x3c48bd7b,0x3d6d3cc4,0xbd0e3d55,
0x3d35bd35,0x3d0e3d55,0xbd6d3cc4,0xbc48bd7b,0xbd80,0x3d7b3c48,0xbcc43d6d,0xbd55bd0e,0x3d353d35,0xbd553d0e,0xbcc4bd6d,0x3d7bbc48,0x3d800000,0xbc483d7b,0xbd6dbcc4,0x3d0ebd55,
0xbd80,0x3d6d3cc4,0xbd353d35,0xbcc4bd6d,0x3d800000,0xbcc43d6d,0xbd35bd35,0x3d6dbcc4,0x3d80,0xbd6dbcc4,0x3d35bd35,0x3cc43d6d,0xbd800000,0x3cc4bd6d,0x3d353d35,0xbd6d3cc4,
0xbd80,0x3d6d3cc4,0xbd353d35,0xbcc4bd6d,0x3d800000,0xbcc43d6d,0xbd35bd35,0x3d6dbcc4,0x3d80,0xbd6dbcc4,0x3d35bd35,0x3cc43d6d,0xbd800000,0x3cc4bd6d,0x3d353d35,0xbd6d3cc4,
0xbd353d35,0xbc48bd7b,0x3d6d3cc4,0xbd553d0e,0x3d800000,0xbd0e3d55,0xbcc4bd6d,0x3d7b3c48,0xbd35bd35,0x3d7bbc48,0xbcc43d6d,0xbd0ebd55,0x3d80,0xbd55bd0e,0x3d6dbcc4,0xbc483d7b,
0x3d35bd35,0x3c483d7b,0xbd6dbcc4,0x3d55bd0e,0xbd800000,0x3d0ebd55,0x3cc43d6d,0xbd7bbc48,0x3d353d35,0xbd7b3c48,0x3cc4bd6d,0x3d0e3d55,0xbd80,0x3d553d0e,0xbd6d3cc4,0x3c48bd7b,
0x3d80,0xbd35bd35,0x3d800000,0xbd353d35,0xbd80,0x3d353d35,0xbd800000,0x3d35bd35,0x3d80,0xbd35bd35,0x3d800000,0xbd353d35,0xbd80,0x3d353d35,0xbd800000,0x3d35bd35,
0x3d80,0xbd35bd35,0x3d800000,0xbd353d35,0xbd80,0x3d353d35,0xbd800000,0x3d35bd35,0x3d80,0xbd35bd35,0x3d800000,0xbd353d35,0xbd80,0x3d353d35,0xbd800000,0x3d35bd35,
0xbd353d35,0x3c48bd7b,0x3cc43d6d,0xbd55bd0e,0xbd80,0x3d0e3d55,0xbd6dbcc4,0x3d7bbc48,0xbd35bd35,0x3d7b3c48,0xbd6d3cc4,0x3d0ebd55,0x3d800000,0xbd553d0e,0x3cc4bd6d,0x3c483d7b,
0x3d35bd35,0xbc483d7b,0xbcc4bd6d,0x3d553d0e,0x3d80,0xbd0ebd55,0x3d6d3cc4,0xbd7b3c48,0x3d353d35,0xbd7bbc48,0x3d6dbcc4,0xbd0e3d55,0xbd800000,0x3d55bd0e,0xbcc43d6d,0xbc48bd7b,
0xbd80,0x3cc43d6d,0xbd35bd35,0x3d6d3cc4,0xbd800000,0x3d6dbcc4,0xbd353d35,0x3cc4bd6d,0x3d80,0xbcc4bd6d,0x3d353d35,0xbd6dbcc4,0x3d800000,0xbd6d3cc4,0x3d35bd35,0xbcc43d6d,
0xbd80,0x3cc43d6d,0xbd35bd35,0x3d6d3cc4,0xbd800000,0x3d6dbcc4,0xbd353d35,0x3cc4bd6d,0x3d80,0xbcc4bd6d,0x3d353d35,0xbd6dbcc4,0x3d800000,0xbd6d3cc4,0x3d35bd35,0xbcc43d6d,
0xbd353d35,0x3d0ebd55,0xbcc43d6d,0x3c48bd7b,0xbd800000,0x3d7bbc48,0xbd6d3cc4,0x3d55bd0e,0xbd35bd35,0x3d553d0e,0xbd6dbcc4,0x3d7b3c48,0xbd80,0x3c483d7b,0xbcc4bd6d,0x3d0e3d55,
0x3d35bd35,0xbd0e3d55,0x3cc4bd6d,0xbc483d7b,0x3d800000,0xbd7b3c48,0x3d6dbcc4,0xbd553d0e,0x3d353d35,0xbd55bd0e,0x3d6d3cc4,0xbd7bbc48,0x3d80,0xbc48bd7b,0x3cc43d6d,0xbd0ebd55,
0xbd800000,0x8000bd80,0x3d800000,0x80003d80,0xbd800000,0x8000bd80,0x3d800000,0x80003d80,0xbd800000,0x8000bd80,0x3d800000,0x80003d80,0xbd800000,0x8000bd80,0x3d800000,0x80003d80,
0xbd800000,0x8000bd80,0x3d800000,0x80003d80,0xbd800000,0x8000bd80,0x3d800000,0x80003d80,0xbd800000,0x8000bd80,0x3d800000,0x80003d80,0xbd800000,0x8000bd80,0x3d800000,0x80003d80,
0xbd35bd35,0x3d55bd0e,0x3cc43d6d,0xbd7b3c48,0xbd800000,0x3c48bd7b,0x3d6d3cc4,0xbd0e3d55,0x3d35bd35,0x3d0e3d55,0xbd6d3cc4,0xbc48bd7b,0x8000bd80,0x3d7b3c48,0xbcc43d6d,0xbd55bd0e,
0x3d353d35,0xbd553d0e,0xbcc4bd6d,0x3d7bbc48,0x3d800000,0xbc483d7b,0xbd6dbcc4,0x3d0ebd55,0xbd353d35,0xbd0ebd55,0x3d6dbcc4,0x3c483d7b,0x80003d80,0xbd7bbc48,0x3cc4bd6d,0x3d553d0e,
0x3d800000,0xbcc43d6d,0xbd35bd35,0x3d6dbcc4,0x80003d80,0xbd6dbcc4,0x3d35bd35,0x3cc43d6d,0xbd800000,0x3cc4bd6d,0x3d353d35,0xbd6d3cc4,0x8000bd80,0x3d6d3cc4,0xbd353d35,0xbcc4bd6d,
0x3d800000,0xbcc43d6d,0xbd35bd35,0x3d6dbcc4,0x80003d80,0xbd6dbcc4,0x3d35bd35,0x3cc43d6d,0xbd800000,0x3cc4bd6d,0x3d353d35,0xbd6d3cc4,0x8000bd80,0x3d6d3cc4,0xbd353d35,0xbcc4bd6d,
0xbd35bd35,0x3d7bbc48,0xbcc43d6d,0xbd0ebd55,0x80003d80,0xbd55bd0e,0x3d6dbcc4,0xbc483d7b,0x3d35bd35,0x3c483d7b,0xbd6dbcc4,0x3d55bd0e,0xbd800000,0x3d0ebd55,0x3cc43d6d,0xbd7bbc48,
0x3d353d35,0xbd7b3c48,0x3cc4bd6d,0x3d0e3d55,0x8000bd80,0x3d553d0e,0xbd6d3cc4,0x3c48bd7b,0xbd353d35,0xbc48bd7b,0x3d6d3cc4,0xbd553d0e,0x3d800000,0xbd0e3d55,0xbcc4bd6d,0x3d7b3c48,
0xbd800000,0x3d35bd35,0x80003d80,0xbd35bd35,0x3d800000,0xbd353d35,0x8000bd80,0x3d353d35,0xbd800000,0x3d35bd35,0x80003d80,0xbd35bd35,0x3d800000,0xbd353d35,0x8000bd80,0x3d353d35,
0xbd800000,0x3d35bd35,0x80003d80,0xbd35bd35,0x3d800000,0xbd353d35,0x8000bd80,0x3d353d35,0xbd800000,0x3d35bd35,0x80003d80,0xbd35bd35,0x3d800000,0xbd353d35,0x8000bd80,0x3d353d35,
0xbd35bd35,0x3d7b3c48,0xbd6d3cc4,0x3d0ebd55,0x3d800000,0xbd553d0e,0x3cc4bd6d,0x3c483d7b,0x3d35bd35,0xbc483d7b,0xbcc4bd6d,0x3d553d0e,0x80003d80,0xbd0ebd55,0x3d6d3cc4,0xbd7b3c48,
0x3d353d35,0xbd7bbc48,0x3d6dbcc4,0xbd0e3d55,0xbd800000,0x3d55bd0e,0xbcc43d6d,0xbc48bd7b,0xbd353d35,0x3c48bd7b,0x3cc43d6d,0xbd55bd0e,0x8000bd80,0x3d0e3d55,0xbd6dbcc4,0x3d7bbc48,
0x3d800000,0xbd6d3cc4,0x3d35bd35,0xbcc43d6d,0x8000bd80,0x3cc43d6d,0xbd35bd35,0x3d6d3cc4,0xbd800000,0x3d6dbcc4,0xbd353d35,0x3cc4bd6d,0x80003d80,0xbcc4bd6d,0x3d353d35,0xbd6dbcc4,
0x3d800000,0xbd6d3cc4,0x3d35bd35,0xbcc43d6d,0x8000bd80,0x3cc43d6d,0xbd35bd35,0x3d6d3cc4,0xbd800000,0x3d6dbcc4,0xbd353d35,0x3cc4bd6d,0x80003d80,0xbcc4bd6d,0x3d353d35,0xbd6dbcc4,
0xbd35bd35,0x3d553d0e,0xbd6dbcc4,0x3d7b3c48,0x8000bd80,0x3c483d7b,0xbcc4bd6d,0x3d0e3d55,0x3d35bd35,0xbd0e3d55,0x3cc4bd6d,0xbc483d7b,0x3d800000,0xbd7b3c48,0x3d6dbcc4,0xbd553d0e,
0x3d353d35,0xbd55bd0e,0x3d6d3cc4,0xbd7bbc48,0x80003d80,0xbc48bd7b,0x3cc43d6d,0xbd0ebd55,0xbd353d35,0x3d0ebd55,0xbcc43d6d,0x3c48bd7b,0xbd800000,0x3d7bbc48,0xbd6d3cc4,0x3d55bd0e,
0x3d80,0xbd80,0x3d80,0xbd80,0x3d80,0xbd80,0x3d80,0xbd80,0x3d80,0xbd80,0x3d80,0xbd80,0x3d80,0xbd80,0x3d80,0xbd80,
0x3d80,0xbd80,0x3d80,0xbd80,0x3d80,0xbd80,0x3d80,0xbd80,0x3d80,0xbd80,0x3d80,0xbd80,0x3d80,0xbd80,0x3d80,0xbd80,
0xbd353d35,0x3d55bd0e,0xbd6d3cc4,0x3d7bbc48,0x3d80,0x3c48bd7b,0xbcc43d6d,0x3d0ebd55,0xbd35bd35,0x3d0e3d55,0xbcc4bd6d,0x3c483d7b,0xbd800000,0x3d7b3c48,0xbd6dbcc4,0x3d553d0e,
0x3d35bd35,0xbd553d0e,0x3d6dbcc4,0xbd7b3c48,0xbd80,0xbc483d7b,0x3cc4bd6d,0xbd0e3d55,0x3d353d35,0xbd0ebd55,0x3cc43d6d,0xbc48bd7b,0x3d800000,0xbd7bbc48,0x3d6d3cc4,0xbd55bd0e,
0xbd80,0xbcc43d6d,0x3d35bd35,0xbd6d3cc4,0x3d800000,0xbd6dbcc4,0x3d353d35,0xbcc4bd6d,0x3d80,0x3cc4bd6d,0xbd353d35,0x3d6dbcc4,0xbd800000,0x3d6d3cc4,0xbd35bd35,0x3cc43d6d,
0xbd80,0xbcc43d6d,0x3d35bd35,0xbd6d3cc4,0x3d800000,0xbd6dbcc4,0x3d353d35,0xbcc4bd6d,0x3d80,0x3cc4bd6d,0xbd353d35,0x3d6dbcc4,0xbd800000,0x3d6d3cc4,0xbd35bd35,0x3cc43d6d,
0xbd353d35,0x3d7bbc48,0xbd6dbcc4,0x3d0e3d55,0x3d800000,0xbd55bd0e,0x3cc43d6d,0x3c48bd7b,0xbd35bd35,0x3c483d7b,0x3cc4bd6d,0xbd553d0e,0x3d80,0x3d0ebd55,0xbd6d3cc4,0x3d7b3c48,
0x3d35bd35,0xbd7b3c48,0x3d6d3cc4,0xbd0ebd55,0xbd800000,0x3d553d0e,0xbcc4bd6d,0xbc483d7b,0x3d353d35,0xbc48bd7b,0xbcc43d6d,0x3d55bd0e,0xbd80,0xbd0e3d55,0x3d6dbcc4,0xbd7bbc48,
0x3d80,0x3d35bd35,0xbd800000,0x3d353d35,0xbd80,0xbd353d35,0x3d800000,0xbd35bd35,0x3d80,0x3d35bd35,0xbd800000,0x3d353d35,0xbd80,0xbd353d35,0x3d800000,0xbd35bd35,
0x3d80,0x3d35bd35,0xbd800000,0x3d353d35,0xbd80,0xbd353d35,0x3d800000,0xbd35bd35,0x3d80,0x3d35bd35,0xbd800000,0x3d353d35,0xbd80,0xbd353d35,0x3d800000,0xbd35bd35,
0xbd353d35,0x3d7b3c48,0xbcc4bd6d,0xbd0e3d55,0xbd80,0xbd553d0e,0x3d6d3cc4,0xbc48bd7b,0xbd35bd35,0xbc483d7b,0x3d6dbcc4,0xbd55bd0e,0x3d800000,0xbd0ebd55,0xbcc43d6d,0x3d7bbc48,
0x3d35bd35,0xbd7bbc48,0x3cc43d6d,0x3d0ebd55,0x3d80,0x3d55bd0e,0xbd6dbcc4,0x3c483d7b,0x3d353d35,0x3c48bd7b,0xbd6d3cc4,0x3d553d0e,0xbd800000,0x3d0e3d55,0x3cc4bd6d,0xbd7b3c48,
0xbd80,0xbd6d3cc4,0x3d353d35,0x3cc4bd6d,0xbd800000,0x3cc43d6d,0x3d35bd35,0xbd6dbcc4,0x3d80,0x3d6dbcc4,0xbd35bd35,0xbcc43d6d,0x3d800000,0xbcc4bd6d,0xbd353d35,0x3d6d3cc4,
0xbd80,0xbd6d3cc4,0x3d353d35,0x3cc4bd6d,0xbd800000,0x3cc43d6d,0x3d35bd35,0xbd6dbcc4,0x3d80,0x3d6dbcc4,0xbd35bd35,0xbcc43d6d,0x3d800000,0xbcc4bd6d,0xbd353d35,0x3d6d3cc4,
0xbd353d35,0x3d553d0e,0x3cc4bd6d,0xbd7bbc48,0xbd800000,0x3c483d7b,0x3d6dbcc4,0xbd0ebd55,0xbd35bd35,0xbd0e3d55,0x3d6d3cc4,0x3c48bd7b,0xbd80,0xbd7b3c48,0x3cc43d6d,0x3d55bd0e,
0x3d35bd35,0xbd55bd0e,0xbcc43d6d,0x3d7b3c48,0x3d800000,0xbc48bd7b,0xbd6d3cc4,0x3d0e3d55,0x3d353d35,0x3d0ebd55,0xbd6dbcc4,0xbc483d7b,0x3d80,0x3d7bbc48,0xbcc4bd6d,0xbd553d0e,
0xbd800000,0x3d800000,0xbd800000,0x3d800000,0xbd800000,0x3d800000,0xbd800000,0x3d800000,0xbd800000,0x3d800000,0xbd800000,0x3d800000,0xbd800000,0x3d800000,0xbd800000,0x3d800000,
0xbd800000,0x3d800000,0xbd800000,0x3d800000,0xbd800000,0x3d800000,0xbd800000,0x3d800000,0xbd800000,0x3d800000,0xbd800000,0x3d800000,0xbd800000,0x3d800000,0xbd800000,0x3d800000,
0xbd35bd35,0x3d0e3d55,0xbcc4bd6d,0x3c483d7b,0xbd800000,0x3d7b3c48,0xbd6dbcc4,0x3d553d0e,0x3d35bd35,0xbd553d0e,0x3d6dbcc4,0xbd7b3c48,0x8000bd80,0xbc483d7b,0x3cc4bd6d,0xbd0e3d55,
0x3d353d35,0xbd0ebd55,0x3cc43d6d,0xbc48bd7b,0x3d800000,0xbd7bbc48,0x3d6d3cc4,0xbd55bd0e,0xbd353d35,0x3d55bd0e,0xbd6d3cc4,0x3d7bbc48,0x80003d80,0x3c48bd7b,0xbcc43d6d,0x3d0ebd55,
0x3d800000,0xbd6dbcc4,0x3d353d35,0xbcc4bd6d,0x80003d80,0x3cc4bd6d,0xbd353d35,0x3d6dbcc4,0xbd800000,0x3d6d3cc4,0xbd35bd35,0x3cc43d6d,0x8000bd80,0xbcc43d6d,0x3d35bd35,0xbd6d3cc4,
0x3d800000,0xbd6dbcc4,0x3d353d35,0xbcc4bd6d,0x80003d80,0x3cc4bd6d,0xbd353d35,0x3d6dbcc4,0xbd800000,0x3d6d3cc4,0xbd35bd35,0x3cc43d6d,0x8000bd80,0xbcc43d6d,0x3d35bd35,0xbd6d3cc4,
0xbd35bd35,0x3c483d7b,0x3cc4bd6d,0xbd553d0e,0x80003d80,0x3d0ebd55,0xbd6d3cc4,0x3d7b3c48,0x3d35bd35,0xbd7b3c48,0x3d6d3cc4,0xbd0ebd55,0xbd800000,0x3d553d0e,0xbcc4bd6d,0xbc483d7b,
0x3d353d35,0xbc48bd7b,0xbcc43d6d,0x3d55bd0e,0x8000bd80,0xbd0e3d55,0x3d6dbcc4,0xbd7bbc48,0xbd353d35,0x3d7bbc48,0xbd6dbcc4,0x3d0e3d55,0x3d800000,0xbd55bd0e,0x3cc43d6d,0x3c48bd7b,
0xbd800000,0x3d353d35,0x8000bd80,0xbd353d35,0x3d800000,0xbd35bd35,0x80003d80,0x3d35bd35,0xbd800000,0x3d353d35,0x8000bd80,0xbd353d35,0x3d800000,0xbd35bd35,0x80003d80,0x3d35bd35,
0xbd800000,0x3d353d35,0x8000bd80,0xbd353d35,0x3d800000,0xbd35bd35,0x80003d80,0x3d35bd35,0xbd800000,0x3d353d35,0x8000bd80,0xbd353d35,0x3d800000,0xbd35bd35,0x80003d80,0x3d35bd35,
0xbd35bd35,0xbc483d7b,0x3d6dbcc4,0xbd55bd0e,0x3d800000,0xbd0ebd55,0xbcc43d6d,0x3d7bbc48,0x3d35bd35,0xbd7bbc48,0x3cc43d6d,0x3d0ebd55,0x80003d80,0x3d55bd0e,0xbd6dbcc4,0x3c483d7b,
0x3d353d35,0x3c48bd7b,0xbd6d3cc4,0x3d553d0e,0xbd800000,0x3d0e3d55,0x3cc4bd6d,0xbd7b3c48,0xbd353d35,0x3d7b3c48,0xbcc4bd6d,0xbd0e3d55,0x8000bd80,0xbd553d0e,0x3d6d3cc4,0xbc48bd7b,
0x3d800000,0xbcc4bd6d,0xbd353d35,0x3d6d3cc4,0x8000bd80,0xbd6d3cc4,0x3d353d35,0x3cc4bd6d,0xbd800000,0x3cc43d6d,0x3d35bd35,0xbd6dbcc4,0x80003d80,0x3d6dbcc4,0xbd35bd35,0xbcc43d6d,
0x3d800000,0xbcc4bd6d,0xbd353d35,0x3d6d3cc4,0x8000bd80,0xbd6d3cc4,0x3d353d35,0x3cc4bd6d,0xbd800000,0x3cc43d6d,0x3d35bd35,0xbd6dbcc4,0x80003d80,0x3d6dbcc4,0xbd35bd35,0xbcc43d6d,
0xbd35bd35,0xbd0e3d55,0x3d6d3cc4,0x3c48bd7b,0x8000bd80,0xbd7b3c48,0x3cc43d6d,0x3d55bd0e,0x3d35bd35,0xbd55bd0e,0xbcc43d6d,0x3d7b3c48,0x3d800000,0xbc48bd7b,0xbd6d3cc4,0x3d0e3d55,
0x3d353d35,0x3d0ebd55,0xbd6dbcc4,0xbc483d7b,0x80003d80,0x3d7bbc48,0xbcc4bd6d,0xbd553d0e,0xbd353d35,0x3d553d0e,0x3cc4bd6d,0xbd7bbc48,0xbd800000,0x3c483d7b,0x3d6dbcc4,0xbd0ebd55,
0x3d80,0x3d800000,0xbd80,0xbd800000,0x3d80,0x3d800000,0xbd80,0xbd800000,0x3d80,0x3d800000,0xbd80,0xbd800000,0x3d80,0x3d800000,0xbd80,0xbd800000,
0x3d80,0x3d800000,0xbd80,0xbd800000,0x3d80,0x3d800000,0xbd80,0xbd800000,0x3d80,0x3d800000,0xbd80,0xbd800000,0x3d80,0x3d800000,0xbd80,0xbd800000,
0xbd353d35,0x3d0e3d55,0x3d6dbcc4,0xbc48bd7b,0x3d80,0x3d7b3c48,0x3cc4bd6d,0xbd55bd0e,0xbd35bd35,0xbd553d0e,0x3cc43d6d,0x3d7bbc48,0xbd800000,0xbc483d7b,0x3d6d3cc4,0x3d0ebd55,
0x3d35bd35,0xbd0ebd55,0xbd6d3cc4,0x3c483d7b,0xbd80,0xbd7bbc48,0xbcc43d6d,0x3d553d0e,0x3d353d35,0x3d55bd0e,0xbcc4bd6d,0xbd7b3c48,0x3d800000,0x3c48bd7b,0xbd6dbcc4,0xbd0e3d55,
0xbd80,0xbd6dbcc4,0xbd353d35,0x3cc43d6d,0x3d800000,0x3cc4bd6d,0xbd35bd35,0xbd6d3cc4,0x3d80,0x3d6d3cc4,0x3d35bd35,0xbcc4bd6d,0xbd800000,0xbcc43d6d,0x3d353d35,0x3d6dbcc4,
0xbd80,0xbd6dbcc4,0xbd353d35,0x3cc43d6d,0x3d800000,0x3cc4bd6d,0xbd35bd35,0xbd6d3cc4,0x3d80,0x3d6d3cc4,0x3d35bd35,0xbcc4bd6d,0xbd800000,0xbcc43d6d,0x3d353d35,0x3d6dbcc4,
0xbd353d35,0x3c483d7b,0x3d6d3cc4,0x3d55bd0e,0x3d800000,0x3d0ebd55,0xbcc4bd6d,0xbd7bbc48,0xbd35bd35,0xbd7b3c48,0xbcc43d6d,0x3d0e3d55,0x3d80,0x3d553d0e,0x3d6dbcc4,0x3c48bd7b,
0x3d35bd35,0xbc48bd7b,0xbd6dbcc4,0xbd553d0e,0xbd800000,0xbd0e3d55,0x3cc43d6d,0x3d7b3c48,0x3d353d35,0x3d7bbc48,0x3cc4bd6d,0xbd0ebd55,0xbd80,0xbd55bd0e,0xbd6d3cc4,0xbc483d7b,
0x3d80,0x3d353d35,0x3d800000,0x3d35bd35,0xbd80,0xbd35bd35,0xbd800000,0xbd353d35,0x3d80,0x3d353d35,0x3d800000,0x3d35bd35,0xbd80,0xbd35bd35,0xbd800000,0xbd353d35,
0x3d80,0x3d353d35,0x3d800000,0x3d35bd35,0xbd80,0xbd35bd35,0xbd800000,0xbd353d35,0x3d80,0x3d353d35,0x3d800000,0x3d35bd35,0xbd80,0xbd35bd35,0xbd800000,0xbd353d35,
0xbd353d35,0xbc483d7b,0x3cc43d6d,0x3d553d0e,0xbd80,0xbd0ebd55,0xbd6dbcc4,0xbd7b3c48,0xbd35bd35,0xbd7bbc48,0xbd6d3cc4,0xbd0e3d55,0x3d800000,0x3d55bd0e,0x3cc4bd6d,0xbc48bd7b,
0x3d35bd35,0x3c48bd7b,0xbcc4bd6d,0xbd55bd0e,0x3d80,0x3d0e3d55,0x3d6d3cc4,0x3d7bbc48,0x3d353d35,0x3d7b3c48,0x3d6dbcc4,0x3d0ebd55,0xbd800000,0xbd553d0e,0xbcc43d6d,0x3c483d7b,
0xbd80,0xbcc4bd6d,0xbd35bd35,0xbd6dbcc4,0xbd800000,0xbd6d3cc4,0xbd353d35,0xbcc43d6d,0x3d80,0x3cc43d6d,0x3d353d35,0x3d6d3cc4,0x3d800000,0x3d6dbcc4,0x3d35bd35,0x3cc4bd6d,
0xbd80,0xbcc4bd6d,0xbd35bd35,0xbd6dbcc4,0xbd800000,0xbd6d3cc4,0xbd353d35,0xbcc43d6d,0x3d80,0x3cc43d6d,0x3d353d35,0x3d6d3cc4,0x3d800000,0x3d6dbcc4,0x3d35bd35,0x3cc4bd6d,
0xbd353d35,0xbd0e3d55,0xbcc43d6d,0xbc483d7b,0xbd800000,0xbd7b3c48,0xbd6d3cc4,0xbd553d0e,0xbd35bd35,0xbd55bd0e,0xbd6dbcc4,0xbd7bbc48,0xbd80,0xbc48bd7b,0xbcc4bd6d,0xbd0ebd55,
0x3d35bd35,0x3d0ebd55,0x3cc4bd6d,0x3c48bd7b,0x3d800000,0x3d7bbc48,0x3d6dbcc4,0x3d55bd0e,0x3d353d35,0x3d553d0e,0x3d6d3cc4,0x3d7b3c48,0x3d80,0x3c483d7b,0x3cc43d6d,0x3d0e3d55,
0xbd800000,0x80003d80,0x3d800000,0x8000bd80,0xbd800000,0x80003d80,0x3d800000,0x8000bd80,0xbd800000,0x80003d80,0x3d800000,0x8000bd80,0xbd800000,0x80003d80,0x3d800000,0x8000bd80,
0xbd800000,0x80003d80,0x3d800000,0x8000bd80,0xbd800000,0x80003d80,0x3d800000,0x8000bd80,0xbd800000,0x80003d80,0x3d800000,0x8000bd80,0xbd800000,0x80003d80,0x3d800000,0x8000bd80,
0xbd35bd35,0xbd553d0e,0x3cc43d6d,0x3d7bbc48,0xbd800000,0xbc483d7b,0x3d6d3cc4,0x3d0ebd55,0x3d35bd35,0xbd0ebd55,0xbd6d3cc4,0x3c483d7b,0x8000bd80,0xbd7bbc48,0xbcc43d6d,0x3d553d0e,
0x3d353d35,0x3d55bd0e,0xbcc4bd6d,0xbd7b3c48,0x3d800000,0x3c48bd7b,0xbd6dbcc4,0xbd0e3d55,0xbd353d35,0x3d0e3d55,0x3d6dbcc4,0xbc48bd7b,0x80003d80,0x3d7b3c48,0x3cc4bd6d,0xbd55bd0e,
0x3d800000,0x3cc4bd6d,0xbd35bd35,0xbd6d3cc4,0x80003d80,0x3d6d3cc4,0x3d35bd35,0xbcc4bd6d,0xbd800000,0xbcc43d6d,0x3d353d35,0x3d6dbcc4,0x8000bd80,0xbd6dbcc4,0xbd353d35,0x3cc43d6d,
0x3d800000,0x3cc4bd6d,0xbd35bd35,0xbd6d3cc4,0x80003d80,0x3d6d3cc4,0x3d35bd35,0xbcc4bd6d,0xbd800000,0xbcc43d6d,0x3d353d35,0x3d6dbcc4,0x8000bd80,0xbd6dbcc4,0xbd353d35,0x3cc43d6d,
0xbd35bd35,0xbd7b3c48,0xbcc43d6d,0x3d0e3d55,0x80003d80,0x3d553d0e,0x3d6dbcc4,0x3c48bd7b,0x3d35bd35,0xbc48bd7b,0xbd6dbcc4,0xbd553d0e,0xbd800000,0xbd0e3d55,0x3cc43d6d,0x3d7b3c48,
0x3d353d35,0x3d7bbc48,0x3cc4bd6d,0xbd0ebd55,0x8000bd80,0xbd55bd0e,0xbd6d3cc4,0xbc483d7b,0xbd353d35,0x3c483d7b,0x3d6d3cc4,0x3d55bd0e,0x3d800000,0x3d0ebd55,0xbcc4bd6d,0xbd7bbc48,
0xbd800000,0xbd353d35,0x80003d80,0x3d353d35,0x3d800000,0x3d35bd35,0x8000bd80,0xbd35bd35,0xbd800000,0xbd353d35,0x80003d80,0x3d353d35,0x3d800000,0x3d35bd35,0x8000bd80,0xbd35bd35,
0xbd800000,0xbd353d35,0x80003d80,0x3d353d35,0x3d800000,0x3d35bd35,0x8000bd80,0xbd35bd35,0xbd800000,0xbd353d35,0x80003d80,0x3d353d35,0x3d800000,0x3d35bd35,0x8000bd80,0xbd35bd35,
0xbd35bd35,0xbd7bbc48,0xbd6d3cc4,0xbd0e3d55,0x3d800000,0x3d55bd0e,0x3cc4bd6d,0xbc48bd7b,0x3d35bd35,0x3c48bd7b,0xbcc4bd6d,0xbd55bd0e,0x80003d80,0x3d0e3d55,0x3d6d3cc4,0x3d7bbc48,
0x3d353d35,0x3d7b3c48,0x3d6dbcc4,0x3d0ebd55,0xbd800000,0xbd553d0e,0xbcc43d6d,0x3c483d7b,0xbd353d35,0xbc483d7b,0x3cc43d6d,0x3d553d0e,0x8000bd80,0xbd0ebd55,0xbd6dbcc4,0xbd7b3c48,
0x3d800000,0x3d6dbcc4,0x3d35bd35,0x3cc4bd6d,0x8000bd80,0xbcc4bd6d,0xbd35bd35,0xbd6dbcc4,0xbd800000,0xbd6d3cc4,0xbd353d35,0xbcc43d6d,0x80003d80,0x3cc43d6d,0x3d353d35,0x3d6d3cc4,
0x3d800000,0x3d6dbcc4,0x3d35bd35,0x3cc4bd6d,0x8000bd80,0xbcc4bd6d,0xbd35bd35,0xbd6dbcc4,0xbd800000,0xbd6d3cc4,0xbd353d35,0xbcc43d6d,0x80003d80,0x3cc43d6d,0x3d353d35,0x3d6d3cc4,
0xbd35bd35,0xbd55bd0e,0xbd6dbcc4,0xbd7bbc48,0x8000bd80,0xbc48bd7b,0xbcc4bd6d,0xbd0ebd55,0x3d35bd35,0x3d0ebd55,0x3cc4bd6d,0x3c48bd7b,0x3d800000,0x3d7bbc48,0x3d6dbcc4,0x3d55bd0e,
0x3d353d35,0x3d553d0e,0x3d6d3cc4,0x3d7b3c48,0x80003d80,0x3c483d7b,0x3cc43d6d,0x3d0e3d55,0xbd353d35,0xbd0e3d55,0xbcc43d6d,0xbc483d7b,0xbd800000,0xbd7b3c48,0xbd6d3cc4,0xbd553d0e,
0x3d80,0xbb493d80,0xbbc93d7f,0xbc163d7d,0xbc483d7b,0xbc793d78,0xbc953d75,0xbcac3d71,0xbcc43d6d,0xbcdb3d67,0xbcf13d62,0xbd043d5c,0xbd0e3d55,0xbd183d4e,0xbd223d46,0xbd2c3d3e,
0xbd353d35,0xbd3e3d2c,0xbd463d22,0xbd4e3d18,0xbd553d0e,0xbd5c3d04,0xbd623cf1,0xbd673cdb,0xbd6d3cc4,0xbd713cac,0xbd753c95,0xbd783c79,0xbd7b3c48,0xbd7d3c16,0xbd7f3bc9,0xbd803b49,
0xbd553d0e,0xbd713cac,0xbd7f3bc9,0xbd7dbc16,0x3d80,0xbc793d78,0xbcf13d62,0xbd2c3d3e,0xbc48bd7b,0x3b49bd80,0x3c95bd75,0x3d04bd5c,0xbd6dbcc4,0xbd4ebd18,0xbd22bd46,0xbcdbbd67,
0x3d7b3c48,0x3d673cdb,0x3d463d22,0x3d183d4e,0x3d35bd35,0x3d5cbd04,0x3d75bc95,0x3d80bb49,0xbd0e3d55,0xbd3e3d2c,0xbd623cf1,0xbd783c79,0x3cc43d6d,0x3c163d7d,0xbbc93d7f,0xbcac3d71,
0x3cc4bd6d,0x3d3ebd2c,0x3d75bc95,0x3d7d3c16,0x3d553d0e,0x3d043d5c,0x3bc93d7f,0xbcac3d71,0x3d80,0xbcdb3d67,0xbd463d22,0xbd783c79,0xbd7bbc48,0xbd4ebd18,0xbcf1bd62,0xbb49bd80,
0x3d6dbcc4,0x3d803b49,0x3d623cf1,0x3d183d4e,0x3c483d7b,0xbc793d78,0xbd223d46,0xbd673cdb,0xbd353d35,0xbd713cac,0xbd7fbbc9,0xbd5cbd04,0xbd0ebd55,0xbc16bd7d,0x3c95bd75,0x3d2cbd3e,
0xbd7b3c48,0xbd67bcdb,0xbcf1bd62,0x3c16bd7d,0x3d6d3cc4,0x3d043d5c,0xbbc93d7f,0xbd2c3d3e,0xbd0ebd55,0x3b49bd80,0x3d22bd46,0x3d78bc79,0x3d80,0xbd183d4e,0xbd753c95,0xbd71bcac,
0x3d553d0e,0x3cac3d71,0xbc953d75,0xbd4e3d18,0xbcc4bd6d,0x3c79bd78,0x3d46bd22,0x3d80bb49,0xbc483d7b,0xbd3e3d2c,0xbd7f3bc9,0xbd5cbd04,0x3d35bd35,0x3d7dbc16,0x3d623cf1,0x3cdb3d67,
0xbd353d35,0xbd80bb49,0xbd22bd46,0x3c16bd7d,0x3d55bd0e,0x3d783c79,0x3cf13d62,0xbcac3d71,0xbd6d3cc4,0xbd67bcdb,0xbc95bd75,0x3d04bd5c,0x3d7bbc48,0x3d4e3d18,0x3bc93d7f,0xbd2c3d3e,
0x3d80,0xbd3e3d2c,0xbd7fbbc9,0xbd18bd4e,0x3c48bd7b,0x3d5cbd04,0x3d753c95,0x3cdb3d67,0xbcc43d6d,0xbd713cac,0xbd62bcf1,0xbc79bd78,0x3d0ebd55,0x3d7dbc16,0x3d463d22,0x3b493d80,
0xbd7bbc48,0xbcacbd71,0x3d22bd46,0x3d7d3c16,0x3d35bd35,0x3d783c79,0x3c953d75,0xbd2c3d3e,0x3d0ebd55,0x3d803b49,0x3cf13d62,0xbd043d5c,0x3cc43d6d,0xbd183d4e,0xbd7fbbc9,0xbcdbbd67,
0x3d55bd0e,0x3d673cdb,0x3bc93d7f,0xbd4e3d18,0x3d80,0xbd5c3d04,0xbd62bcf1,0xbb49bd80,0x3c483d7b,0xbd3e3d2c,0xbd75bc95,0xbc79bd78,0xbd6dbcc4,0xbc16bd7d,0x3d46bd22,0x3d713cac,
0x3d6dbcc4,0x3d2c3d3e,0xbcf13d62,0xbd7dbc16,0xbc48bd7b,0x3d5cbd04,0x3d463d22,0xbcac3d71,0xbd353d35,0xbd67bcdb,0x3bc9bd7f,0x3d78bc79,0x3d0e3d55,0xbd183d4e,0xbd75bc95,0xbb49bd80,
0x3cc4bd6d,0x3d803b49,0x3c953d75,0xbd4e3d18,0xbd55bd0e,0x3c79bd78,0x3d7fbbc9,0x3cdb3d67,0x3d80,0xbd713cac,0xbd22bd46,0x3d04bd5c,0x3d7b3c48,0x3c163d7d,0xbd623cf1,0xbd3ebd2c,
0xbd55bd0e,0x3cdbbd67,0x3d753c95,0xbc163d7d,0xbcc4bd6d,0x3d5cbd04,0x3d223d46,0xbd2c3d3e,0x3c48bd7b,0x3d803b49,0x3bc93d7f,0xbd783c79,0x3d35bd35,0x3d4e3d18,0xbcf13d62,0xbd71bcac,
0x3d7bbc48,0x3cac3d71,0xbd623cf1,0xbd18bd4e,0x3d6d3cc4,0xbc793d78,0xbd7fbbc9,0xbb49bd80,0x3d0e3d55,0xbd3e3d2c,0xbd46bd22,0x3d04bd5c,0x3d80,0xbd7d3c16,0xbc95bd75,0x3d67bcdb,
0xbd800000,0xbd80bb49,0xbd7fbbc9,0xbd7dbc16,0xbd7bbc48,0xbd78bc79,0xbd75bc95,0xbd71bcac,0xbd6dbcc4,0xbd67bcdb,0xbd62bcf1,0xbd5cbd04,0xbd55bd0e,0xbd4ebd18,0xbd46bd22,0xbd3ebd2c,
0xbd35bd35,0xbd2cbd3e,0xbd22bd46,0xbd18bd4e,0xbd0ebd55,0xbd04bd5c,0xbcf1bd62,0xbcdbbd67,0xbcc4bd6d,0xbcacbd71,0xbc95bd75,0xbc79bd78,0xbc48bd7b,0xbc16bd7d,0xbbc9bd7f,0xbb49bd80,
0xbd0ebd55,0xbcacbd71,0xbbc9bd7f,0x3c16bd7d,0xbd800000,0xbd78bc79,0xbd62bcf1,0xbd3ebd2c,0x3d7bbc48,0x3d803b49,0x3d753c95,0x3d5c3d04,0x3cc4bd6d,0x3d18bd4e,0x3d46bd22,0x3d67bcdb,
0xbc483d7b,0xbcdb3d67,0xbd223d46,0xbd4e3d18,0x3d353d35,0x3d043d5c,0x3c953d75,0x3b493d80,0xbd55bd0e,0xbd2cbd3e,0xbcf1bd62,0xbc79bd78,0xbd6d3cc4,0xbd7d3c16,0xbd7fbbc9,0xbd71bcac,
0x3d6d3cc4,0x3d2c3d3e,0x3c953d75,0xbc163d7d,0xbd0e3d55,0xbd5c3d04,0xbd7f3bc9,0xbd71bcac,0xbd800000,0xbd67bcdb,0xbd22bd46,0xbc79bd78,0x3c48bd7b,0x3d18bd4e,0x3d62bcf1,0x3d80bb49,
0x3cc43d6d,0xbb493d80,0xbcf13d62,0xbd4e3d18,0xbd7b3c48,0xbd78bc79,0xbd46bd22,0xbcdbbd67,0xbd35bd35,0xbcacbd71,0x3bc9bd7f,0x3d04bd5c,0x3d55bd0e,0x3d7dbc16,0x3d753c95,0x3d3e3d2c,
0xbc48bd7b,0x3cdbbd67,0x3d62bcf1,0x3d7d3c16,0xbcc43d6d,0xbd5c3d04,0xbd7fbbc9,0xbd3ebd2c,0x3d55bd0e,0x3d803b49,0x3d463d22,0x3c793d78,0xbd800000,0xbd4ebd18,0xbc95bd75,0x3cacbd71,
0xbd0e3d55,0xbd713cac,0xbd75bc95,0xbd18bd4e,0x3d6dbcc4,0x3d783c79,0x3d223d46,0x3b493d80,0xbd7bbc48,0xbd2cbd3e,0xbbc9bd7f,0x3d04bd5c,0x3d353d35,0x3c163d7d,0xbcf13d62,0xbd673cdb,
0xbd35bd35,0x3b49bd80,0x3d46bd22,0x3d7d3c16,0x3d0e3d55,0xbc793d78,0xbd623cf1,0xbd71bcac,0xbcc4bd6d,0x3cdbbd67,0x3d75bc95,0x3d5c3d04,0x3c483d7b,0xbd183d4e,0xbd7f3bc9,0xbd3ebd2c,
0xbd800000,0xbd2cbd3e,0x3bc9bd7f,0x3d4ebd18,0x3d7b3c48,0x3d043d5c,0xbc953d75,0xbd673cdb,0xbd6dbcc4,0xbcacbd71,0x3cf1bd62,0x3d78bc79,0x3d553d0e,0x3c163d7d,0xbd223d46,0xbd803b49,
0x3c48bd7b,0x3d71bcac,0x3d463d22,0xbc163d7d,0x3d353d35,0xbc793d78,0xbd753c95,0xbd3ebd2c,0x3d553d0e,0xbb493d80,0xbd623cf1,0xbd5cbd04,0xbd6d3cc4,0xbd4ebd18,0x3bc9bd7f,0x3d67bcdb,
0x3d0e3d55,0xbcdb3d67,0xbd7f3bc9,0xbd18bd4e,0xbd800000,0xbd04bd5c,0x3cf1bd62,0x3d80bb49,0xbd7b3c48,0xbd2cbd3e,0x3c95bd75,0x3d78bc79,0x3cc4bd6d,0x3d7dbc16,0x3d223d46,0xbcac3d71,
0x3cc43d6d,0xbd3e3d2c,0xbd62bcf1,0x3c16bd7d,0x3d7bbc48,0x3d043d5c,0xbd223d46,0xbd71bcac,0xbd35bd35,0x3cdbbd67,0x3d7f3bc9,0x3c793d78,0xbd553d0e,0xbd4ebd18,0x3c95bd75,0x3d80bb49,
0x3d6d3cc4,0xbb493d80,0xbd753c95,0xbd18bd4e,0x3d0ebd55,0x3d783c79,0x3bc93d7f,0xbd673cdb,0xbd800000,0xbcacbd71,0x3d46bd22,0x3d5c3d04,0xbc483d7b,0xbd7d3c16,0xbcf1bd62,0x3d2cbd3e,
0x3d0ebd55,0x3d673cdb,0xbc953d75,0xbd7dbc16,0x3d6dbcc4,0x3d043d5c,0xbd463d22,0xbd3ebd2c,0x3d7b3c48,0xbb493d80,0xbd7f3bc9,0xbc79bd78,0x3d353d35,0xbd183d4e,0xbd62bcf1,0x3cacbd71,
0x3c483d7b,0xbd713cac,0xbcf1bd62,0x3d4ebd18,0xbcc43d6d,0xbd78bc79,0x3bc9bd7f,0x3d80bb49,0xbd553d0e,0xbd2cbd3e,0x3d22bd46,0x3d5c3d04,0xbd800000,0xbc16bd7d,0x3d75bc95,0x3cdb3d67,
0x3d80,0xbd80bb49,0x3bc9bd7f,0x3d7d3c16,0xbc483d7b,0xbd78bc79,0x3c95bd75,0x3d713cac,0xbcc43d6d,0xbd67bcdb,0x3cf1bd62,0x3d5c3d04,0xbd0e3d55,0xbd4ebd18,0x3d22bd46,0x3d3e3d2c,
0xbd353d35,0xbd2cbd3e,0x3d46bd22,0x3d183d4e,0xbd553d0e,0xbd04bd5c,0x3d62bcf1,0x3cdb3d67,0xbd6d3cc4,0xbcacbd71,0x3d75bc95,0x3c793d78,0xbd7b3c48,0xbc16bd7d,0x3d7fbbc9,0x3b493d80,
0xbd553d0e,0xbcacbd71,0x3d7fbbc9,0xbc163d7d,0x3d80,0xbd78bc79,0x3cf1bd62,0x3d3e3d2c,0xbc48bd7b,0x3d803b49,0xbc953d75,0xbd5cbd04,0xbd6dbcc4,0x3d18bd4e,0x3d223d46,0xbd673cdb,
0x3d7b3c48,0xbcdb3d67,0xbd46bd22,0x3d4ebd18,0x3d35bd35,0x3d043d5c,0xbd753c95,0xbb49bd80,0xbd0e3d55,0xbd2cbd3e,0x3d62bcf1,0x3c793d78,0x3cc43d6d,0xbd7d3c16,0x3bc9bd7f,0x3d713cac,
0x3cc4bd6d,0x3d2c3d3e,0xbd753c95,0x3c16bd7d,0x3d553d0e,0xbd5c3d04,0xbbc9bd7f,0x3d713cac,0x3d80,0xbd67bcdb,0x3d46bd22,0x3c793d78,0xbd7bbc48,0x3d18bd4e,0x3cf13d62,0xbd803b49,
0x3d6dbcc4,0xbb493d80,0xbd62bcf1,0x3d4ebd18,0x3c483d7b,0xbd78bc79,0x3d22bd46,0x3cdb3d67,0xbd353d35,0xbcacbd71,0x3d7f3bc9,0xbd043d5c,0xbd0ebd55,0x3d7dbc16,0xbc953d75,0xbd3ebd2c,
0xbd7b3c48,0x3cdbbd67,0x3cf13d62,0xbd7dbc16,0x3d6d3cc4,0xbd5c3d04,0x3bc9bd7f,0x3d3e3d2c,0xbd0ebd55,0x3d803b49,0xbd223d46,0xbc79bd78,0x3d80,0xbd4ebd18,0x3d75bc95,0xbcac3d71,
0x3d553d0e,0xbd713cac,0x3c95bd75,0x3d183d4e,0xbcc4bd6d,0x3d783c79,0xbd463d22,0xbb49bd80,0xbc483d7b,0xbd2cbd3e,0x3d7fbbc9,0xbd043d5c,0x3d35bd35,0x3c163d7d,0xbd62bcf1,0x3d67bcdb,
0xbd353d35,0x3b49bd80,0x3d223d46,0xbd7dbc16,0x3d55bd0e,0xbc793d78,0xbcf1bd62,0x3d713cac,0xbd6d3cc4,0x3cdbbd67,0x3c953d75,0xbd5cbd04,0x3d7bbc48,0xbd183d4e,0xbbc9bd7f,0x3d3e3d2c,
0x3d80,0xbd2cbd3e,0x3d7f3bc9,0xbd4e3d18,0x3c48bd7b,0x3d043d5c,0xbd75bc95,0x3d67bcdb,0xbcc43d6d,0xbcacbd71,0x3d623cf1,0xbd783c79,0x3d0ebd55,0x3c163d7d,0xbd46bd22,0x3d80bb49,
0xbd7bbc48,0x3d71bcac,0xbd223d46,0x3c16bd7d,0x3d35bd35,0xbc793d78,0xbc95bd75,0x3d3e3d2c,0x3d0ebd55,0xbb493d80,0xbcf1bd62,0x3d5c3d04,0x3cc43d6d,0xbd4ebd18,0x3d7f3bc9,0xbd673cdb,
0x3d55bd0e,0xbcdb3d67,0xbbc9bd7f,0x3d183d4e,0x3d80,0xbd04bd5c,0x3d623cf1,0xbd803b49,0x3c483d7b,0xbd2cbd3e,0x3d753c95,0xbd783c79,0xbd6dbcc4,0x3d7dbc16,0xbd463d22,0x3cacbd71,
0x3d6dbcc4,0xbd3e3d2c,0x3cf1bd62,0xbc163d7d,0xbc48bd7b,0x3d043d5c,0xbd46bd22,0x3d713cac,0xbd353d35,0x3cdbbd67,0xbbc93d7f,0xbc79bd78,0x3d0e3d55,0xbd4ebd18,0x3d753c95,0xbd803b49,
0x3cc4bd6d,0xbb493d80,0xbc95bd75,0x3d183d4e,0xbd55bd0e,0x3d783c79,0xbd7f3bc9,0x3d67bcdb,0x3d80,0xbcacbd71,0x3d223d46,0xbd5cbd04,0x3d7b3c48,0xbd7d3c16,0x3d62bcf1,0xbd2c3d3e,
0xbd55bd0e,0x3d673cdb,0xbd75bc95,0x3d7d3c16,0xbcc4bd6d,0x3d043d5c,0xbd22bd46,0x3d3e3d2c,0x3c48bd7b,0xbb493d80,0xbbc9bd7f,0x3c793d78,0x3d35bd35,0xbd183d4e,0x3cf1bd62,0xbcac3d71,
0x3d7bbc48,0xbd713cac,0x3d62bcf1,0xbd4e3d18,0x3d6d3cc4,0xbd78bc79,0x3d7f3bc9,0xbd803b49,0x3d0e3d55,0xbd2cbd3e,0x3d463d22,0xbd5cbd04,0x3d80,0xbc16bd7d,0x3c953d75,0xbcdbbd67,
0xbd800000,0x3b49bd80,0x3d7f3bc9,0xbc163d7d,0xbd7bbc48,0x3c79bd78,0x3d753c95,0xbcac3d71,0xbd6dbcc4,0x3cdbbd67,0x3d623cf1,0xbd043d5c,0xbd55bd0e,0x3d18bd4e,0x3d463d22,0xbd2c3d3e,
0xbd35bd35,0x3d3ebd2c,0x3d223d46,0xbd4e3d18,0xbd0ebd55,0x3d5cbd04,0x3cf13d62,0xbd673cdb,0xbcc4bd6d,0x3d71bcac,0x3c953d75,0xbd783c79,0xbc48bd7b,0x3d7dbc16,0x3bc93d7f,0xbd803b49,
0xbd0ebd55,0x3d71bcac,0x3bc93d7f,0xbd7dbc16,0xbd800000,0x3c79bd78,0x3d623cf1,0xbd2c3d3e,0x3d7bbc48,0xbb493d80,0xbd75bc95,0x3d04bd5c,0x3cc4bd6d,0x3d4e3d18,0xbd463d22,0xbcdbbd67,
0xbc483d7b,0xbd67bcdb,0x3d22bd46,0x3d183d4e,0x3d353d35,0xbd5c3d04,0xbc95bd75,0x3d80bb49,0xbd55bd0e,0x3d3ebd2c,0x3cf13d62,0xbd783c79,0xbd6d3cc4,0xbc16bd7d,0x3d7f3bc9,0xbcac3d71,
0x3d6d3cc4,0xbd3e3d2c,0xbc95bd75,0x3d7d3c16,0xbd0e3d55,0xbd04bd5c,0x3d7fbbc9,0xbcac3d71,0xbd800000,0x3cdbbd67,0x3d223d46,0xbd783c79,0x3c48bd7b,0x3d4e3d18,0xbd623cf1,0xbb49bd80,
0x3cc43d6d,0xbd80bb49,0x3cf1bd62,0x3d183d4e,0xbd7b3c48,0x3c79bd78,0x3d463d22,0xbd673cdb,0xbd35bd35,0x3d71bcac,0xbbc93d7f,0xbd5cbd04,0x3d55bd0e,0x3c163d7d,0xbd75bc95,0x3d2cbd3e,
0xbc48bd7b,0x3d673cdb,0xbd623cf1,0x3c16bd7d,0xbcc43d6d,0xbd04bd5c,0x3d7f3bc9,0xbd2c3d3e,0x3d55bd0e,0xbb493d80,0xbd46bd22,0x3d78bc79,0xbd800000,0x3d18bd4e,0x3c953d75,0xbd71bcac,
0xbd0e3d55,0xbcacbd71,0x3d753c95,0xbd4e3d18,0x3d6dbcc4,0xbc793d78,0xbd22bd46,0x3d80bb49,0xbd7bbc48,0x3d3ebd2c,0x3bc93d7f,0xbd5cbd04,0x3d353d35,0xbd7d3c16,0x3cf1bd62,0x3cdb3d67,
0xbd35bd35,0x3d803b49,0xbd463d22,0x3c16bd7d,0x3d0e3d55,0xbd78bc79,0x3d62bcf1,0xbcac3d71,0xbcc4bd6d,0x3d673cdb,0xbd753c95,0x3d04bd5c,0x3c483d7b,0xbd4ebd18,0x3d7fbbc9,0xbd2c3d3e,
0xbd800000,0x3d3ebd2c,0xbbc93d7f,0xbd18bd4e,0x3d7b3c48,0xbd5c3d04,0x3c95bd75,0x3cdb3d67,0xbd6dbcc4,0x3d71bcac,0xbcf13d62,0xbc79bd78,0x3d553d0e,0xbd7d3c16,0x3d22bd46,0x3b493d80,
0x3c48bd7b,0x3cac3d71,0xbd46bd22,0x3d7d3c16,0x3d353d35,0xbd78bc79,0x3d75bc95,0xbd2c3d3e,0x3d553d0e,0xbd80bb49,0x3d62bcf1,0xbd043d5c,0xbd6d3cc4,0x3d18bd4e,0xbbc93d7f,0xbcdbbd67,
0x3d0e3d55,0xbd67bcdb,0x3d7fbbc9,0xbd4e3d18,0xbd800000,0x3d5cbd04,0xbcf13d62,0xbb49bd80,0xbd7b3c48,0x3d3ebd2c,0xbc953d75,0xbc79bd78,0x3cc4bd6d,0x3c163d7d,0xbd22bd46,0x3d713cac,
0x3cc43d6d,0xbd2cbd3e,0x3d623cf1,0xbd7dbc16,0x3d7bbc48,0xbd5c3d04,0x3d22bd46,0xbcac3d71,0xbd35bd35,0x3d673cdb,0xbd7fbbc9,0x3d78bc79,0xbd553d0e,0x3d18bd4e,0xbc953d75,0xbb49bd80,
0x3d6d3cc4,0xbd80bb49,0x3d75bc95,0xbd4e3d18,0x3d0ebd55,0xbc793d78,0xbbc9bd7f,0x3cdb3d67,0xbd800000,0x3d71bcac,0xbd463d22,0x3d04bd5c,0xbc483d7b,0xbc16bd7d,0x3cf13d62,0xbd3ebd2c,
0x3d0ebd55,0xbcdb3d67,0x3c95bd75,0xbc163d7d,0x3d6dbcc4,0xbd5c3d04,0x3d46bd22,0xbd2c3d3e,0x3d7b3c48,0xbd80bb49,0x3d7fbbc9,0xbd783c79,0x3d353d35,0xbd4ebd18,0x3d623cf1,0xbd71bcac,
0x3c483d7b,0xbcacbd71,0x3cf13d62,0xbd18bd4e,0xbcc43d6d,0x3c79bd78,0xbbc93d7f,0xbb49bd80,0xbd553d0e,0x3d3ebd2c,0xbd223d46,0x3d04bd5c,0xbd800000,0x3d7dbc16,0xbd753c95,0x3d67bcdb,
0x3d80,0x3b49bd80,0xbbc93d7f,0x3c16bd7d,0xbc483d7b,0x3c79bd78,0xbc953d75,0x3cacbd71,0xbcc43d6d,0x3cdbbd67,0xbcf13d62,0x3d04bd5c,0xbd0e3d55,0x3d18bd4e,0xbd223d46,0x3d2cbd3e,
0xbd353d35,0x3d3ebd2c,0xbd463d22,0x3d4ebd18,0xbd553d0e,0x3d5cbd04,0xbd623cf1,0x3d67bcdb,0xbd6d3cc4,0x3d71bcac,0xbd753c95,0x3d78bc79,0xbd7b3c48,0x3d7dbc16,0xbd7f3bc9,0x3d80bb49,
0xbd553d0e,0x3d71bcac,0xbd7f3bc9,0x3d7d3c16,0x3d80,0x3c79bd78,0xbcf13d62,0x3d2cbd3e,0xbc48bd7b,0xbb493d80,0x3c95bd75,0xbd043d5c,0xbd6dbcc4,0x3d4e3d18,0xbd22bd46,0x3cdb3d67,
0x3d7b3c48,0xbd67bcdb,0x3d463d22,0xbd18bd4e,0x3d35bd35,0xbd5c3d04,0x3d75bc95,0xbd803b49,0xbd0e3d55,0x3d3ebd2c,0xbd623cf1,0x3d78bc79,0x3cc43d6d,0xbc16bd7d,0xbbc93d7f,0x3cacbd71,
0x3cc4bd6d,0xbd3e3d2c,0x3d75bc95,0xbd7dbc16,0x3d553d0e,0xbd04bd5c,0x3bc93d7f,0x3cacbd71,0x3d80,0x3cdbbd67,0xbd463d22,0x3d78bc79,0xbd7bbc48,0x3d4e3d18,0xbcf1bd62,0x3b493d80,
0x3d6dbcc4,0xbd80bb49,0x3d623cf1,0xbd18bd4e,0x3c483d7b,0x3c79bd78,0xbd223d46,0x3d67bcdb,0xbd353d35,0x3d71bcac,0xbd7fbbc9,0x3d5c3d04,0xbd0ebd55,0x3c163d7d,0x3c95bd75,0xbd2c3d3e,
0xbd7b3c48,0x3d673cdb,0xbcf1bd62,0xbc163d7d,0x3d6d3cc4,0xbd04bd5c,0xbbc93d7f,0x3d2cbd3e,0xbd0ebd55,0xbb493d80,0x3d22bd46,0xbd783c79,0x3d80,0x3d18bd4e,0xbd753c95,0x3d713cac,
0x3d553d0e,0xbcacbd71,0xbc953d75,0x3d4ebd18,0xbcc4bd6d,0xbc793d78,0x3d46bd22,0xbd803b49,0xbc483d7b,0x3d3ebd2c,0xbd7f3bc9,0x3d5c3d04,0x3d35bd35,0xbd7d3c16,0x3d623cf1,0xbcdbbd67,
0xbd353d35,0x3d803b49,0xbd22bd46,0xbc163d7d,0x3d55bd0e,0xbd78bc79,0x3cf13d62,0x3cacbd71,0xbd6d3cc4,0x3d673cdb,0xbc95bd75,0xbd043d5c,0x3d7bbc48,0xbd4ebd18,0x3bc93d7f,0x3d2cbd3e,
0x3d80,0x3d3ebd2c,0xbd7fbbc9,0x3d183d4e,0x3c48bd7b,0xbd5c3d04,0x3d753c95,0xbcdbbd67,0xbcc43d6d,0x3d71bcac,0xbd62bcf1,0x3c793d78,0x3d0ebd55,0xbd7d3c16,0x3d463d22,0xbb49bd80,
0xbd7bbc48,0x3cac3d71,0x3d22bd46,0xbd7dbc16,0x3d35bd35,0xbd78bc79,0x3c953d75,0x3d2cbd3e,0x3d0ebd55,0xbd80bb49,0x3cf13d62,0x3d04bd5c,0x3cc43d6d,0x3d18bd4e,0xbd7fbbc9,0x3cdb3d67,
0x3d55bd0e,0xbd67bcdb,0x3bc93d7f,0x3d4ebd18,0x3d80,0x3d5cbd04,0xbd62bcf1,0x3b493d80,0x3c483d7b,0x3d3ebd2c,0xbd75bc95,0x3c793d78,0xbd6dbcc4,0x3c163d7d,0x3d46bd22,0xbd71bcac,
0x3d6dbcc4,0xbd2cbd3e,0xbcf13d62,0x3d7d3c16,0xbc48bd7b,0xbd5c3d04,0x3d463d22,0x3cacbd71,0xbd353d35,0x3d673cdb,0x3bc9bd7f,0xbd783c79,0x3d0e3d55,0x3d18bd4e,0xbd75bc95,0x3b493d80,
0x3cc4bd6d,0xbd80bb49,0x3c953d75,0x3d4ebd18,0xbd55bd0e,0xbc793d78,0x3d7fbbc9,0xbcdbbd67,0x3d80,0x3d71bcac,0xbd22bd46,0xbd043d5c,0x3d7b3c48,0xbc16bd7d,0xbd623cf1,0x3d3e3d2c,
0xbd55bd0e,0xbcdb3d67,0x3d753c95,0x3c16bd7d,0xbcc4bd6d,0xbd5c3d04,0x3d223d46,0x3d2cbd3e,0x3c48bd7b,0xbd80bb49,0x3bc93d7f,0x3d78bc79,0x3d35bd35,0xbd4ebd18,0xbcf13d62,0x3d713cac,
0x3d7bbc48,0xbcacbd71,0xbd623cf1,0x3d183d4e,0x3d6d3cc4,0x3c79bd78,0xbd7fbbc9,0x3b493d80,0x3d0e3d55,0x3d3ebd2c,0xbd46bd22,0xbd043d5c,0x3d80,0x3d7dbc16,0xbc95bd75,0xbd673cdb,
0xbd800000,0x3d803b49,0xbd7fbbc9,0x3d7d3c16,0xbd7bbc48,0x3d783c79,0xbd75bc95,0x3d713cac,0xbd6dbcc4,0x3d673cdb,0xbd62bcf1,0x3d5c3d04,0xbd55bd0e,0x3d4e3d18,0xbd46bd22,0x3d3e3d2c,
0xbd35bd35,0x3d2c3d3e,0xbd22bd46,0x3d183d4e,0xbd0ebd55,0x3d043d5c,0xbcf1bd62,0x3cdb3d67,0xbcc4bd6d,0x3cac3d71,0xbc95bd75,0x3c793d78,0xbc48bd7b,0x3c163d7d,0xbbc9bd7f,0x3b493d80,
0xbd0ebd55,0x3cac3d71,0xbbc9bd7f,0xbc163d7d,0xbd800000,0x3d783c79,0xbd62bcf1,0x3d3e3d2c,0x3d7bbc48,0xbd80bb49,0x3d753c95,0xbd5cbd04,0x3cc4bd6d,0xbd183d4e,0x3d46bd22,0xbd673cdb,
0xbc483d7b,0x3cdbbd67,0xbd223d46,0x3d4ebd18,0x3d353d35,0xbd04bd5c,0x3c953d75,0xbb49bd80,0xbd55bd0e,0x3d2c3d3e,0xbcf1bd62,0x3c793d78,0xbd6d3cc4,0x3d7dbc16,0xbd7fbbc9,0x3d713cac,
0x3d6d3cc4,0xbd2cbd3e,0x3c953d75,0x3c16bd7d,0xbd0e3d55,0x3d5cbd04,0xbd7f3bc9,0x3d713cac,0xbd800000,0x3d673cdb,0xbd22bd46,0x3c793d78,0x3c48bd7b,0xbd183d4e,0x3d62bcf1,0xbd803b49,
0x3cc43d6d,0x3b49bd80,0xbcf13d62,0x3d4ebd18,0xbd7b3c48,0x3d783c79,0xbd46bd22,0x3cdb3d67,0xbd35bd35,0x3cac3d71,0x3bc9bd7f,0xbd043d5c,0x3d55bd0e,0xbd7d3c16,0x3d753c95,0xbd3ebd2c,
0xbc48bd7b,0xbcdb3d67,0x3d62bcf1,0xbd7dbc16,0xbcc43d6d,0x3d5cbd04,0xbd7fbbc9,0x3d3e3d2c,0x3d55bd0e,0xbd80bb49,0x3d463d22,0xbc79bd78,0xbd800000,0x3d4e3d18,0xbc95bd75,0xbcac3d71,
0xbd0e3d55,0x3d71bcac,0xbd75bc95,0x3d183d4e,0x3d6dbcc4,0xbd78bc79,0x3d223d46,0xbb49bd80,0xbd7bbc48,0x3d2c3d3e,0xbbc9bd7f,0xbd043d5c,0x3d353d35,0xbc16bd7d,0xbcf13d62,0x3d67bcdb,
0xbd35bd35,0xbb493d80,0x3d46bd22,0xbd7dbc16,0x3d0e3d55,0x3c79bd78,0xbd623cf1,0x3d713cac,0xbcc4bd6d,0xbcdb3d67,0x3d75bc95,0xbd5cbd04,0x3c483d7b,0x3d18bd4e,0xbd7f3bc9,0x3d3e3d2c,
0xbd800000,0x3d2c3d3e,0x3bc9bd7f,0xbd4e3d18,0x3d7b3c48,0xbd04bd5c,0xbc953d75,0x3d67bcdb,0xbd6dbcc4,0x3cac3d71,0x3cf1bd62,0xbd783c79,0x3d553d0e,0xbc16bd7d,0xbd223d46,0x3d80bb49,
0x3c48bd7b,0xbd713cac,0x3d463d22,0x3c16bd7d,0x3d353d35,0x3c79bd78,0xbd753c95,0x3d3e3d2c,0x3d553d0e,0x3b49bd80,0xbd623cf1,0x3d5c3d04,0xbd6d3cc4,0x3d4e3d18,0x3bc9bd7f,0xbd673cdb,
0x3d0e3d55,0x3cdbbd67,0xbd7f3bc9,0x3d183d4e,0xbd800000,0x3d043d5c,0x3cf1bd62,0xbd803b49,0xbd7b3c48,0x3d2c3d3e,0x3c95bd75,0xbd783c79,0x3cc4bd6d,0xbd7d3c16,0x3d223d46,0x3cacbd71,
0x3cc43d6d,0x3d3ebd2c,0xbd62bcf1,0xbc163d7d,0x3d7bbc48,0xbd04bd5c,0xbd223d46,0x3d713cac,0xbd35bd35,0xbcdb3d67,0x3d7f3bc9,0xbc79bd78,0xbd553d0e,0x3d4e3d18,0x3c95bd75,0xbd803b49,
0x3d6d3cc4,0x3b49bd80,0xbd753c95,0x3d183d4e,0x3d0ebd55,0xbd78bc79,0x3bc93d7f,0x3d67bcdb,0xbd800000,0x3cac3d71,0x3d46bd22,0xbd5cbd04,0xbc483d7b,0x3d7dbc16,0xbcf1bd62,0xbd2c3d3e,
0x3d0ebd55,0xbd67bcdb,0xbc953d75,0x3d7d3c16,0x3d6dbcc4,0xbd04bd5c,0xbd463d22,0x3d3e3d2c,0x3d7b3c48,0x3b49bd80,0xbd7f3bc9,0x3c793d78,0x3d353d35,0x3d18bd4e,0xbd62bcf1,0xbcac3d71,
0x3c483d7b,0x3d71bcac,0xbcf1bd62,0xbd4e3d18,0xbcc43d6d,0x3d783c79,0x3bc9bd7f,0xbd803b49,0xbd553d0e,0x3d2c3d3e,0x3d22bd46,0xbd5cbd04,0xbd800000,0x3c163d7d,0x3d75bc95,0xbcdbbd67,
0x3d80,0x3d803b49,0x3bc9bd7f,0xbd7dbc16,0xbc483d7b,0x3d783c79,0x3c95bd75,0xbd71bcac,0xbcc43d6d,0x3d673cdb,0x3cf1bd62,0xbd5cbd04,0xbd0e3d55,0x3d4e3d18,0x3d22bd46,0xbd3ebd2c,
0xbd353d35,0x3d2c3d3e,0x3d46bd22,0xbd18bd4e,0xbd553d0e,0x3d043d5c,0x3d62bcf1,0xbcdbbd67,0xbd6d3cc4,0x3cac3d71,0x3d75bc95,0xbc79bd78,0xbd7b3c48,0x3c163d7d,0x3d7fbbc9,0xbb49bd80,
0xbd553d0e,0x3cac3d71,0x3d7fbbc9,0x3c16bd7d,0x3d80,0x3d783c79,0x3cf1bd62,0xbd3ebd2c,0xbc48bd7b,0xbd80bb49,0xbc953d75,0x3d5c3d04,0xbd6dbcc4,0xbd183d4e,0x3d223d46,0x3d67bcdb,
0x3d7b3c48,0x3cdbbd67,0xbd46bd22,0xbd4e3d18,0x3d35bd35,0xbd04bd5c,0xbd753c95,0x3b493d80,0xbd0e3d55,0x3d2c3d3e,0x3d62bcf1,0xbc79bd78,0x3cc43d6d,0x3d7dbc16,0x3bc9bd7f,0xbd71bcac,
0x3cc4bd6d,0xbd2cbd3e,0xbd753c95,0xbc163d7d,0x3d553d0e,0x3d5cbd04,0xbbc9bd7f,0xbd71bcac,0x3d80,0x3d673cdb,0x3d46bd22,0xbc79bd78,0xbd7bbc48,0xbd183d4e,0x3cf13d62,0x3d80bb49,
0x3d6dbcc4,0x3b49bd80,0xbd62bcf1,0xbd4e3d18,0x3c483d7b,0x3d783c79,0x3d22bd46,0xbcdbbd67,0xbd353d35,0x3cac3d71,0x3d7f3bc9,0x3d04bd5c,0xbd0ebd55,0xbd7d3c16,0xbc953d75,0x3d3e3d2c,
0xbd7b3c48,0xbcdb3d67,0x3cf13d62,0x3d7d3c16,0x3d6d3cc4,0x3d5cbd04,0x3bc9bd7f,0xbd3ebd2c,0xbd0ebd55,0xbd80bb49,0xbd223d46,0x3c793d78,0x3d80,0x3d4e3d18,0x3d75bc95,0x3cacbd71,
0x3d553d0e,0x3d71bcac,0x3c95bd75,0xbd18bd4e,0xbcc4bd6d,0xbd78bc79,0xbd463d22,0x3b493d80,0xbc483d7b,0x3d2c3d3e,0x3d7fbbc9,0x3d04bd5c,0x3d35bd35,0xbc16bd7d,0xbd62bcf1,0xbd673cdb,
0xbd353d35,0xbb493d80,0x3d223d46,0x3d7d3c16,0x3d55bd0e,0x3c79bd78,0xbcf1bd62,0xbd71bcac,0xbd6d3cc4,0xbcdb3d67,0x3c953d75,0x3d5c3d04,0x3d7bbc48,0x3d18bd4e,0xbbc9bd7f,0xbd3ebd2c,
0x3d80,0x3d2c3d3e,0x3d7f3bc9,0x3d4ebd18,0x3c48bd7b,0xbd04bd5c,0xbd75bc95,0xbd673cdb,0xbcc43d6d,0x3cac3d71,0x3d623cf1,0x3d78bc79,0x3d0ebd55,0xbc16bd7d,0xbd46bd22,0xbd803b49,
0xbd7bbc48,0xbd713cac,0xbd223d46,0xbc163d7d,0x3d35bd35,0x3c79bd78,0xbc95bd75,0xbd3ebd2c,0x3d0ebd55,0x3b49bd80,0xbcf1bd62,0xbd5cbd04,0x3cc43d6d,0x3d4e3d18,0x3d7f3bc9,0x3d67bcdb,
0x3d55bd0e,0x3cdbbd67,0xbbc9bd7f,0xbd18bd4e,0x3d80,0x3d043d5c,0x3d623cf1,0x3d80bb49,0x3c483d7b,0x3d2c3d3e,0x3d753c95,0x3d78bc79,0xbd6dbcc4,0xbd7d3c16,0xbd463d22,0xbcac3d71,
0x3d6dbcc4,0x3d3ebd2c,0x3cf1bd62,0x3c16bd7d,0xbc48bd7b,0xbd04bd5c,0xbd46bd22,0xbd71bcac,0xbd353d35,0xbcdb3d67,0xbbc93d7f,0x3c793d78,0x3d0e3d55,0x3d4e3d18,0x3d753c95,0x3d80bb49,
0x3cc4bd6d,0x3b49bd80,0xbc95bd75,0xbd18bd4e,0xbd55bd0e,0xbd78bc79,0xbd7f3bc9,0xbd673cdb,0x3d80,0x3cac3d71,0x3d223d46,0x3d5c3d04,0x3d7b3c48,0x3d7dbc16,0x3d62bcf1,0x3d2cbd3e,
0xbd55bd0e,0xbd67bcdb,0xbd75bc95,0xbd7dbc16,0xbcc4bd6d,0xbd04bd5c,0xbd22bd46,0xbd3ebd2c,0x3c48bd7b,0x3b49bd80,0xbbc9bd7f,0xbc79bd78,0x3d35bd35,0x3d18bd4e,0x3cf1bd62,0x3cacbd71,
0x3d7bbc48,0x3d71bcac,0x3d62bcf1,0x3d4ebd18,0x3d6d3cc4,0x3d783c79,0x3d7f3bc9,0x3d80bb49,0x3d0e3d55,0x3d2c3d3e,0x3d463d22,0x3d5c3d04,0x3d80,0x3c163d7d,0x3c953d75,0x3cdb3d67,
0xbd800000,0xbb493d80,0x3d7f3bc9,0x3c16bd7d,0xbd7bbc48,0xbc793d78,0x3d753c95,0x3cacbd71,0xbd6dbcc4,0xbcdb3d67,0x3d623cf1,0x3d04bd5c,0xbd55bd0e,0xbd183d4e,0x3d463d22,0x3d2cbd3e,
0xbd35bd35,0xbd3e3d2c,0x3d223d46,0x3d4ebd18,0xbd0ebd55,0xbd5c3d04,0x3cf13d62,0x3d67bcdb,0xbcc4bd6d,0xbd713cac,0x3c953d75,0x3d78bc79,0xbc48bd7b,0xbd7d3c16,0x3bc93d7f,0x3d80bb49,
0xbd0ebd55,0xbd713cac,0x3bc93d7f,0x3d7d3c16,0xbd800000,0xbc793d78,0x3d623cf1,0x3d2cbd3e,0x3d7bbc48,0x3b49bd80,0xbd75bc95,0xbd043d5c,0x3cc4bd6d,0xbd4ebd18,0xbd463d22,0x3cdb3d67,
0xbc483d7b,0x3d673cdb,0x3d22bd46,0xbd18bd4e,0x3d353d35,0x3d5cbd04,0xbc95bd75,0xbd803b49,0xbd55bd0e,0xbd3e3d2c,0x3cf13d62,0x3d78bc79,0xbd6d3cc4,0x3c163d7d,0x3d7f3bc9,0x3cacbd71,
0x3d6d3cc4,0x3d3ebd2c,0xbc95bd75,0xbd7dbc16,0xbd0e3d55,0x3d043d5c,0x3d7fbbc9,0x3cacbd71,0xbd800000,0xbcdb3d67,0x3d223d46,0x3d78bc79,0x3c48bd7b,0xbd4ebd18,0xbd623cf1,0x3b493d80,
0x3cc43d6d,0x3d803b49,0x3cf1bd62,0xbd18bd4e,0xbd7b3c48,0xbc793d78,0x3d463d22,0x3d67bcdb,0xbd35bd35,0xbd713cac,0xbbc93d7f,0x3d5c3d04,0x3d55bd0e,0xbc16bd7d,0xbd75bc95,0xbd2c3d3e,
0xbc48bd7b,0xbd67bcdb,0xbd623cf1,0xbc163d7d,0xbcc43d6d,0x3d043d5c,0x3d7f3bc9,0x3d2cbd3e,0x3d55bd0e,0x3b49bd80,0xbd46bd22,0xbd783c79,0xbd800000,0xbd183d4e,0x3c953d75,0x3d713cac,
0xbd0e3d55,0x3cac3d71,0x3d753c95,0x3d4ebd18,0x3d6dbcc4,0x3c79bd78,0xbd22bd46,0xbd803b49,0xbd7bbc48,0xbd3e3d2c,0x3bc93d7f,0x3d5c3d04,0x3d353d35,0x3d7dbc16,0x3cf1bd62,0xbcdbbd67,
0xbd35bd35,0xbd80bb49,0xbd463d22,0xbc163d7d,0x3d0e3d55,0x3d783c79,0x3d62bcf1,0x3cacbd71,0xbcc4bd6d,0xbd67bcdb,0xbd753c95,0xbd043d5c,0x3c483d7b,0x3d4e3d18,0x3d7fbbc9,0x3d2cbd3e,
0xbd800000,0xbd3e3d2c,0xbbc93d7f,0x3d183d4e,0x3d7b3c48,0x3d5cbd04,0x3c95bd75,0xbcdbbd67,0xbd6dbcc4,0xbd713cac,0xbcf13d62,0x3c793d78,0x3d553d0e,0x3d7dbc16,0x3d22bd46,0xbb49bd80,
0x3c48bd7b,0xbcacbd71,0xbd46bd22,0xbd7dbc16,0x3d353d35,0x3d783c79,0x3d75bc95,0x3d2cbd3e,0x3d553d0e,0x3d803b49,0x3d62bcf1,0x3d04bd5c,0xbd6d3cc4,0xbd183d4e,0xbbc93d7f,0x3cdb3d67,
0x3d0e3d55,0x3d673cdb,0x3d7fbbc9,0x3d4ebd18,0xbd800000,0xbd5c3d04,0xbcf13d62,0x3b493d80,0xbd7b3c48,0xbd3e3d2c,0xbc953d75,0x3c793d78,0x3cc4bd6d,0xbc16bd7d,0xbd22bd46,0xbd71bcac,
0x3cc43d6d,0x3d2c3d3e,0x3d623cf1,0x3d7d3c16,0x3d7bbc48,0x3d5cbd04,0x3d22bd46,0x3cacbd71,0xbd35bd35,0xbd67bcdb,0xbd7fbbc9,0xbd783c79,0xbd553d0e,0xbd183d4e,0xbc953d75,0x3b493d80,
0x3d6d3cc4,0x3d803b49,0x3d75bc95,0x3d4ebd18,0x3d0ebd55,0x3c79bd78,0xbbc9bd7f,0xbcdbbd67,0xbd800000,0xbd713cac,0xbd463d22,0xbd043d5c,0xbc483d7b,0x3c163d7d,0x3cf13d62,0x3d3e3d2c,
0x3d0ebd55,0x3cdbbd67,0x3c95bd75,0x3c16bd7d,0x3d6dbcc4,0x3d5cbd04,0x3d46bd22,0x3d2cbd3e,0x3d7b3c48,0x3d803b49,0x3d7fbbc9,0x3d78bc79,0x3d353d35,0x3d4e3d18,0x3d623cf1,0x3d713cac,
0x3c483d7b,0x3cac3d71,0x3cf13d62,0x3d183d4e,0xbcc43d6d,0xbc793d78,0xbbc93d7f,0x3b493d80,0xbd553d0e,0xbd3e3d2c,0xbd223d46,0xbd043d5c,0xbd800000,0xbd7d3c16,0xbd753c95,0xbd673cdb,
0x3d80,0xbbc93d7f,0xbc483d7b,0xbc953d75,0xbcc43d6d,0xbcf13d62,0xbd0e3d55,0xbd223d46,0xbd353d35,0xbd463d22,0xbd553d0e,0xbd623cf1,0xbd6d3cc4,0xbd753c95,0xbd7b3c48,0xbd7f3bc9,
0xbd800000,0xbd7fbbc9,0xbd7bbc48,0xbd75bc95,0xbd6dbcc4,0xbd62bcf1,0xbd55bd0e,0xbd46bd22,0xbd35bd35,0xbd22bd46,0xbd0ebd55,0xbcf1bd62,0xbcc4bd6d,0xbc95bd75,0xbc48bd7b,0xbbc9bd7f,
0xbd6d3cc4,0xbd7f3bc9,0xbd7bbc48,0xbd62bcf1,0x3d80,0xbc953d75,0xbd0e3d55,0xbd463d22,0x3cc4bd6d,0x3d22bd46,0x3d55bd0e,0x3d75bc95,0xbd35bd35,0xbcf1bd62,0xbc48bd7b,0x3bc9bd7f,
0x3cc43d6d,0x3bc93d7f,0xbc483d7b,0xbcf13d62,0x3d800000,0x3d753c95,0x3d553d0e,0x3d223d46,0xbd6dbcc4,0xbd46bd22,0xbd0ebd55,0xbc95bd75,0xbd353d35,0xbd623cf1,0xbd7b3c48,0xbd7fbbc9,
0x3d35bd35,0x3d75bc95,0x3d7b3c48,0x3d463d22,0x3cc43d6d,0xbbc93d7f,0xbd0e3d55,0xbd623cf1,0x3d80,0xbcf13d62,0xbd553d0e,0xbd7f3bc9,0xbd6dbcc4,0xbd22bd46,0xbc48bd7b,0x3c95bd75,
0x3d353d35,0x3c953d75,0xbc483d7b,0xbd223d46,0xbd6d3cc4,0xbd7fbbc9,0xbd55bd0e,0xbcf1bd62,0xbd800000,0xbd62bcf1,0xbd0ebd55,0xbbc9bd7f,0x3cc4bd6d,0x3d46bd22,0x3d7bbc48,0x3d753c95,
0xbd6dbcc4,0xbcf1bd62,0x3c48bd7b,0x3d46bd22,0x3d353d35,0x3bc93d7f,0xbd0e3d55,0xbd753c95,0xbcc4bd6d,0x3c95bd75,0x3d55bd0e,0x3d7f3bc9,0x3d80,0xbd223d46,0xbd7b3c48,0xbd62bcf1,
0xbcc43d6d,0xbd623cf1,0xbd7bbc48,0xbd22bd46,0x3d35bd35,0x3d7fbbc9,0x3d553d0e,0x3c953d75,0xbd6d3cc4,0xbd75bc95,0xbd0ebd55,0x3bc9bd7f,0x3d800000,0x3d463d22,0x3c483d7b,0xbcf13d62,
0xbd800000,0xbd22bd46,0x3c48bd7b,0x3d62bcf1,0x3d6d3cc4,0x3c953d75,0xbd0e3d55,0xbd7f3bc9,0xbd35bd35,0x3bc9bd7f,0x3d55bd0e,0x3d753c95,0x3cc43d6d,0xbcf13d62,0xbd7b3c48,0xbd46bd22,
0x3d80,0xbd463d22,0xbd7bbc48,0xbcf1bd62,0x3cc4bd6d,0x3d75bc95,0x3d553d0e,0x3bc93d7f,0xbd353d35,0xbd7fbbc9,0xbd0ebd55,0x3c95bd75,0x3d6dbcc4,0x3d623cf1,0x3c483d7b,0xbd223d46,
0xbcc4bd6d,0x3d22bd46,0x3d7b3c48,0x3c953d75,0x3d800000,0x3cf13d62,0xbd0e3d55,0xbd7fbbc9,0x3d6d3cc4,0x3bc93d7f,0xbd553d0e,0xbd62bcf1,0xbd353d35,0xbd75bc95,0xbc48bd7b,0x3d46bd22,
0x3d6dbcc4,0x3d463d22,0xbc483d7b,0xbd753c95,0x3d80,0xbd623cf1,0xbd55bd0e,0x3bc9bd7f,0xbcc43d6d,0xbd7f3bc9,0xbd0ebd55,0x3cf1bd62,0xbd35bd35,0x3c95bd75,0x3d7bbc48,0x3d223d46,
0x3d353d35,0xbcf13d62,0xbd7bbc48,0xbbc9bd7f,0x3d6dbcc4,0x3d223d46,0xbd0e3d55,0xbd75bc95,0xbd800000,0xbc95bd75,0x3d55bd0e,0x3d463d22,0xbcc43d6d,0xbd7fbbc9,0xbc48bd7b,0x3d62bcf1,
0x3d35bd35,0x3d623cf1,0xbc483d7b,0xbd7f3bc9,0xbcc4bd6d,0x3d46bd22,0x3d553d0e,0xbc953d75,0x3d80,0xbd753c95,0xbd0ebd55,0x3d22bd46,0x3d6d3cc4,0xbbc93d7f,0xbd7b3c48,0xbcf1bd62,
0x3cc4bd6d,0x3d753c95,0xbc483d7b,0xbd7fbbc9,0x3d35bd35,0x3d463d22,0xbd0e3d55,0xbd62bcf1,0x3d6dbcc4,0x3cf13d62,0xbd553d0e,0xbd22bd46,0x3d800000,0x3bc93d7f,0xbd7b3c48,0xbc95bd75,
0x3d6d3cc4,0xbc953d75,0xbd7bbc48,0x3bc9bd7f,0x3d353d35,0xbd223d46,0xbd55bd0e,0x3cf1bd62,0x3cc43d6d,0xbd623cf1,0xbd0ebd55,0x3d46bd22,0x3d80,0xbd7f3bc9,0xbc48bd7b,0x3d75bc95,
0xbd800000,0xbd7fbbc9,0xbd7bbc48,0xbd75bc95,0xbd6dbcc4,0xbd62bcf1,0xbd55bd0e,0xbd46bd22,0xbd35bd35,0xbd22bd46,0xbd0ebd55,0xbcf1bd62,0xbcc4bd6d,0xbc95bd75,0xbc48bd7b,0xbbc9bd7f,
0x8000bd80,0x3bc9bd7f,0x3c48bd7b,0x3c95bd75,0x3cc4bd6d,0x3cf1bd62,0x3d0ebd55,0x3d22bd46,0x3d35bd35,0x3d46bd22,0x3d55bd0e,0x3d62bcf1,0x3d6dbcc4,0x3d75bc95,0x3d7bbc48,0x3d7fbbc9,
0xbcc4bd6d,0xbbc9bd7f,0x3c48bd7b,0x3cf1bd62,0xbd800000,0xbd75bc95,0xbd55bd0e,0xbd22bd46,0x3d6d3cc4,0x3d463d22,0x3d0e3d55,0x3c953d75,0x3d35bd35,0x3d62bcf1,0x3d7bbc48,0x3d7f3bc9,
0xbd6d3cc4,0xbd7f3bc9,0xbd7bbc48,0xbd62bcf1,0x80003d80,0xbc953d75,0xbd0e3d55,0xbd463d22,0x3cc4bd6d,0x3d22bd46,0x3d55bd0e,0x3d75bc95,0xbd35bd35,0xbcf1bd62,0xbc48bd7b,0x3bc9bd7f,
0x3d353d35,0x3c953d75,0xbc483d7b,0xbd223d46,0xbd6d3cc4,0xbd7fbbc9,0xbd55bd0e,0xbcf1bd62,0xbd800000,0xbd62bcf1,0xbd0ebd55,0xbbc9bd7f,0x3cc4bd6d,0x3d46bd22,0x3d7bbc48,0x3d753c95,
0xbd353d35,0xbd753c95,0xbd7bbc48,0xbd46bd22,0xbcc4bd6d,0x3bc9bd7f,0x3d0ebd55,0x3d62bcf1,0x8000bd80,0x3cf1bd62,0x3d55bd0e,0x3d7fbbc9,0x3d6d3cc4,0x3d223d46,0x3c483d7b,0xbc953d75,
0x3cc4bd6d,0x3d62bcf1,0x3d7b3c48,0x3d223d46,0xbd353d35,0xbd7f3bc9,0xbd55bd0e,0xbc95bd75,0x3d6dbcc4,0x3d753c95,0x3d0e3d55,0xbbc93d7f,0xbd800000,0xbd46bd22,0xbc48bd7b,0x3cf1bd62,
0xbd6dbcc4,0xbcf1bd62,0x3c48bd7b,0x3d46bd22,0x3d353d35,0x3bc93d7f,0xbd0e3d55,0xbd753c95,0xbcc4bd6d,0x3c95bd75,0x3d55bd0e,0x3d7f3bc9,0x80003d80,0xbd223d46,0xbd7b3c48,0xbd62bcf1,
0x8000bd80,0x3d46bd22,0x3d7b3c48,0x3cf13d62,0xbcc43d6d,0xbd753c95,0xbd55bd0e,0xbbc9bd7f,0x3d35bd35,0x3d7f3bc9,0x3d0e3d55,0xbc953d75,0xbd6d3cc4,0xbd62bcf1,0xbc48bd7b,0x3d22bd46,
0xbd800000,0xbd22bd46,0x3c48bd7b,0x3d62bcf1,0x3d6d3cc4,0x3c953d75,0xbd0e3d55,0xbd7f3bc9,0xbd35bd35,0x3bc9bd7f,0x3d55bd0e,0x3d753c95,0x3cc43d6d,0xbcf13d62,0xbd7b3c48,0xbd46bd22,
0x3d6dbcc4,0x3d463d22,0xbc483d7b,0xbd753c95,0x80003d80,0xbd623cf1,0xbd55bd0e,0x3bc9bd7f,0xbcc43d6d,0xbd7f3bc9,0xbd0ebd55,0x3cf1bd62,0xbd35bd35,0x3c95bd75,0x3d7bbc48,0x3d223d46,
0x3cc43d6d,0xbd223d46,0xbd7bbc48,0xbc95bd75,0xbd800000,0xbcf1bd62,0x3d0ebd55,0x3d7f3bc9,0xbd6dbcc4,0xbbc9bd7f,0x3d55bd0e,0x3d623cf1,0x3d35bd35,0x3d753c95,0x3c483d7b,0xbd463d22,
0xbd353d35,0xbd62bcf1,0x3c48bd7b,0x3d7fbbc9,0x3cc43d6d,0xbd463d22,0xbd55bd0e,0x3c95bd75,0x8000bd80,0x3d75bc95,0x3d0e3d55,0xbd223d46,0xbd6dbcc4,0x3bc9bd7f,0x3d7bbc48,0x3cf13d62,
0x3d353d35,0xbcf13d62,0xbd7bbc48,0xbbc9bd7f,0x3d6dbcc4,0x3d223d46,0xbd0e3d55,0xbd75bc95,0xbd800000,0xbc95bd75,0x3d55bd0e,0x3d463d22,0xbcc43d6d,0xbd7fbbc9,0xbc48bd7b,0x3d62bcf1,
0x3d6d3cc4,0xbc953d75,0xbd7bbc48,0x3bc9bd7f,0x3d353d35,0xbd223d46,0xbd55bd0e,0x3cf1bd62,0x3cc43d6d,0xbd623cf1,0xbd0ebd55,0x3d46bd22,0x80003d80,0xbd7f3bc9,0xbc48bd7b,0x3d75bc95,
0xbcc43d6d,0xbd75bc95,0x3c48bd7b,0x3d7f3bc9,0xbd353d35,0xbd46bd22,0x3d0ebd55,0x3d623cf1,0xbd6d3cc4,0xbcf1bd62,0x3d55bd0e,0x3d223d46,0xbd800000,0xbbc9bd7f,0x3d7bbc48,0x3c953d75,
0x3d80,0xbd7fbbc9,0x3c48bd7b,0x3d753c95,0xbcc43d6d,0xbd62bcf1,0x3d0ebd55,0x3d463d22,0xbd353d35,0xbd22bd46,0x3d55bd0e,0x3cf13d62,0xbd6d3cc4,0xbc95bd75,0x3d7bbc48,0x3bc93d7f,
0xbd800000,0x3bc9bd7f,0x3d7b3c48,0xbc953d75,0xbd6dbcc4,0x3cf1bd62,0x3d553d0e,0xbd223d46,0xbd35bd35,0x3d46bd22,0x3d0e3d55,0xbd623cf1,0xbcc4bd6d,0x3d75bc95,0x3c483d7b,0xbd7f3bc9,
0xbd6d3cc4,0xbbc9bd7f,0x3d7b3c48,0xbcf13d62,0x3d80,0xbd75bc95,0x3d0ebd55,0x3d223d46,0x3cc4bd6d,0x3d463d22,0xbd553d0e,0xbc95bd75,0xbd35bd35,0x3d62bcf1,0x3c483d7b,0xbd7fbbc9,
0x3cc43d6d,0xbd7f3bc9,0x3c48bd7b,0x3d623cf1,0x3d800000,0xbc953d75,0xbd55bd0e,0x3d46bd22,0xbd6dbcc4,0x3d22bd46,0x3d0e3d55,0xbd753c95,0xbd353d35,0xbcf1bd62,0x3d7bbc48,0xbbc93d7f,
0x3d35bd35,0x3c953d75,0xbd7bbc48,0x3d22bd46,0x3cc43d6d,0xbd7fbbc9,0x3d0ebd55,0x3cf13d62,0x3d80,0xbd62bcf1,0x3d55bd0e,0x3bc93d7f,0xbd6dbcc4,0x3d46bd22,0x3c483d7b,0xbd75bc95,
0x3d353d35,0xbd753c95,0x3c48bd7b,0x3d463d22,0xbd6d3cc4,0x3bc9bd7f,0x3d553d0e,0xbd623cf1,0xbd800000,0x3cf1bd62,0x3d0e3d55,0xbd7f3bc9,0x3cc4bd6d,0x3d223d46,0xbd7b3c48,0x3c95bd75,
0xbd6dbcc4,0x3d62bcf1,0xbc483d7b,0xbd22bd46,0x3d353d35,0xbd7f3bc9,0x3d0ebd55,0x3c953d75,0xbcc4bd6d,0x3d753c95,0xbd553d0e,0x3bc9bd7f,0x3d80,0xbd46bd22,0x3d7bbc48,0xbcf13d62,
0xbcc43d6d,0xbcf1bd62,0x3d7b3c48,0xbd463d22,0x3d35bd35,0x3bc93d7f,0xbd55bd0e,0x3d75bc95,0xbd6d3cc4,0x3c95bd75,0x3d0e3d55,0xbd7fbbc9,0x3d800000,0xbd223d46,0xbc48bd7b,0x3d623cf1,
0xbd800000,0x3d46bd22,0xbc483d7b,0xbcf1bd62,0x3d6d3cc4,0xbd753c95,0x3d0ebd55,0x3bc93d7f,0xbd35bd35,0x3d7f3bc9,0xbd553d0e,0x3c95bd75,0x3cc43d6d,0xbd62bcf1,0x3d7bbc48,0xbd223d46,
0x3d80,0xbd22bd46,0x3d7b3c48,0xbd623cf1,0x3cc4bd6d,0x3c953d75,0xbd55bd0e,0x3d7fbbc9,0xbd353d35,0x3bc9bd7f,0x3d0e3d55,0xbd75bc95,0x3d6dbcc4,0xbcf13d62,0xbc48bd7b,0x3d463d22,
0xbcc4bd6d,0x3d463d22,0xbd7bbc48,0x3d75bc95,0x3d800000,0xbd623cf1,0x3d0ebd55,0xbbc93d7f,0x3d6d3cc4,0xbd7f3bc9,0x3d55bd0e,0xbcf13d62,0xbd353d35,0x3c95bd75,0x3c483d7b,0xbd22bd46,
0x3d6dbcc4,0xbd223d46,0x3c48bd7b,0x3c953d75,0x3d80,0xbcf1bd62,0x3d553d0e,0xbd7fbbc9,0xbcc43d6d,0xbbc9bd7f,0x3d0e3d55,0xbd62bcf1,0xbd35bd35,0x3d753c95,0xbd7b3c48,0x3d46bd22,
0x3d353d35,0xbd62bcf1,0x3d7b3c48,0xbd7f3bc9,0x3d6dbcc4,0xbd463d22,0x3d0ebd55,0xbc953d75,0xbd800000,0x3d75bc95,0xbd553d0e,0x3d22bd46,0xbcc43d6d,0x3bc9bd7f,0x3c483d7b,0xbcf1bd62,
0x3d35bd35,0xbcf13d62,0x3c48bd7b,0x3bc93d7f,0xbcc4bd6d,0x3d223d46,0xbd55bd0e,0x3d753c95,0x3d80,0xbc95bd75,0x3d0e3d55,0xbd46bd22,0x3d6d3cc4,0xbd7fbbc9,0x3d7bbc48,0xbd623cf1,
0x3cc4bd6d,0xbc953d75,0x3c48bd7b,0xbbc93d7f,0x3d35bd35,0xbd223d46,0x3d0ebd55,0xbcf13d62,0x3d6dbcc4,0xbd623cf1,0x3d55bd0e,0xbd463d22,0x3d800000,0xbd7f3bc9,0x3d7bbc48,0xbd753c95,
0x3d6d3cc4,0xbd75bc95,0x3d7b3c48,0xbd7fbbc9,0x3d353d35,0xbd46bd22,0x3d553d0e,0xbd62bcf1,0x3cc43d6d,0xbcf1bd62,0x3d0e3d55,0xbd22bd46,0x3d80,0xbbc9bd7f,0x3c483d7b,0xbc95bd75,
0xbd800000,0x3bc9bd7f,0x3d7b3c48,0xbc953d75,0xbd6dbcc4,0x3cf1bd62,0x3d553d0e,0xbd223d46,0xbd35bd35,0x3d46bd22,0x3d0e3d55,0xbd623cf1,0xbcc4bd6d,0x3d75bc95,0x3c483d7b,0xbd7f3bc9,
0x8000bd80,0x3d7f3bc9,0xbc483d7b,0xbd75bc95,0x3cc4bd6d,0x3d623cf1,0xbd0e3d55,0xbd46bd22,0x3d35bd35,0x3d223d46,0xbd553d0e,0xbcf1bd62,0x3d6dbcc4,0x3c953d75,0xbd7b3c48,0xbbc9bd7f,
0xbcc4bd6d,0x3d7fbbc9,0xbc483d7b,0xbd62bcf1,0xbd800000,0x3c95bd75,0x3d553d0e,0xbd463d22,0x3d6d3cc4,0xbd223d46,0xbd0ebd55,0x3d75bc95,0x3d35bd35,0x3cf13d62,0xbd7b3c48,0x3bc9bd7f,
0xbd6d3cc4,0xbbc9bd7f,0x3d7b3c48,0xbcf13d62,0x80003d80,0xbd75bc95,0x3d0ebd55,0x3d223d46,0x3cc4bd6d,0x3d463d22,0xbd553d0e,0xbc95bd75,0xbd35bd35,0x3d62bcf1,0x3c483d7b,0xbd7fbbc9,
0x3d353d35,0xbd753c95,0x3c48bd7b,0x3d463d22,0xbd6d3cc4,0x3bc9bd7f,0x3d553d0e,0xbd623cf1,0xbd800000,0x3cf1bd62,0x3d0e3d55,0xbd7f3bc9,0x3cc4bd6d,0x3d223d46,0xbd7b3c48,0x3c95bd75,
0xbd353d35,0xbc95bd75,0x3d7b3c48,0xbd223d46,0xbcc4bd6d,0x3d7f3bc9,0xbd0e3d55,0xbcf1bd62,0x8000bd80,0x3d623cf1,0xbd553d0e,0xbbc9bd7f,0x3d6d3cc4,0xbd463d22,0xbc48bd7b,0x3d753c95,
0x3cc4bd6d,0x3cf13d62,0xbd7bbc48,0x3d46bd22,0xbd353d35,0xbbc9bd7f,0x3d553d0e,0xbd753c95,0x3d6dbcc4,0xbc953d75,0xbd0ebd55,0x3d7f3bc9,0xbd800000,0x3d22bd46,0x3c483d7b,0xbd62bcf1,
0xbd6dbcc4,0x3d62bcf1,0xbc483d7b,0xbd22bd46,0x3d353d35,0xbd7f3bc9,0x3d0ebd55,0x3c953d75,0xbcc4bd6d,0x3d753c95,0xbd553d0e,0x3bc9bd7f,0x80003d80,0xbd46bd22,0x3d7bbc48,0xbcf13d62,
0x8000bd80,0x3d223d46,0xbd7bbc48,0x3d62bcf1,0xbcc43d6d,0xbc95bd75,0x3d553d0e,0xbd7f3bc9,0x3d35bd35,0xbbc93d7f,0xbd0ebd55,0x3d753c95,0xbd6d3cc4,0x3cf1bd62,0x3c483d7b,0xbd46bd22,
0xbd800000,0x3d46bd22,0xbc483d7b,0xbcf1bd62,0x3d6d3cc4,0xbd753c95,0x3d0ebd55,0x3bc93d7f,0xbd35bd35,0x3d7f3bc9,0xbd553d0e,0x3c95bd75,0x3cc43d6d,0xbd62bcf1,0x3d7bbc48,0xbd223d46,
0x3d6dbcc4,0xbd223d46,0x3c48bd7b,0x3c953d75,0x80003d80,0xbcf1bd62,0x3d553d0e,0xbd7fbbc9,0xbcc43d6d,0xbbc9bd7f,0x3d0e3d55,0xbd62bcf1,0xbd35bd35,0x3d753c95,0xbd7b3c48,0x3d46bd22,
0x3cc43d6d,0xbd46bd22,0x3d7b3c48,0xbd753c95,0xbd800000,0x3d62bcf1,0xbd0e3d55,0x3bc9bd7f,0xbd6dbcc4,0x3d7fbbc9,0xbd553d0e,0x3cf1bd62,0x3d35bd35,0xbc953d75,0xbc48bd7b,0x3d223d46,
0xbd353d35,0x3cf1bd62,0xbc483d7b,0xbbc9bd7f,0x3cc43d6d,0xbd22bd46,0x3d553d0e,0xbd75bc95,0x8000bd80,0x3c953d75,0xbd0ebd55,0x3d463d22,0xbd6dbcc4,0x3d7f3bc9,0xbd7b3c48,0x3d62bcf1,
0x3d353d35,0xbd62bcf1,0x3d7b3c48,0xbd7f3bc9,0x3d6dbcc4,0xbd463d22,0x3d0ebd55,0xbc953d75,0xbd800000,0x3d75bc95,0xbd553d0e,0x3d22bd46,0xbcc43d6d,0x3bc9bd7f,0x3c483d7b,0xbcf1bd62,
0x3d6d3cc4,0xbd75bc95,0x3d7b3c48,0xbd7fbbc9,0x3d353d35,0xbd46bd22,0x3d553d0e,0xbd62bcf1,0x3cc43d6d,0xbcf1bd62,0x3d0e3d55,0xbd22bd46,0x80003d80,0xbbc9bd7f,0x3c483d7b,0xbc95bd75,
0xbcc43d6d,0x3c95bd75,0xbc483d7b,0x3bc9bd7f,0xbd353d35,0x3d22bd46,0xbd0e3d55,0x3cf1bd62,0xbd6d3cc4,0x3d62bcf1,0xbd553d0e,0x3d46bd22,0xbd800000,0x3d7fbbc9,0xbd7b3c48,0x3d75bc95,
0x3d80,0x3bc9bd7f,0xbc483d7b,0x3c95bd75,0xbcc43d6d,0x3cf1bd62,0xbd0e3d55,0x3d22bd46,0xbd353d35,0x3d46bd22,0xbd553d0e,0x3d62bcf1,0xbd6d3cc4,0x3d75bc95,0xbd7b3c48,0x3d7fbbc9,
0xbd800000,0x3d7f3bc9,0xbd7bbc48,0x3d753c95,0xbd6dbcc4,0x3d623cf1,0xbd55bd0e,0x3d463d22,0xbd35bd35,0x3d223d46,0xbd0ebd55,0x3cf13d62,0xbcc4bd6d,0x3c953d75,0xbc48bd7b,0x3bc93d7f,
0xbd6d3cc4,0x3d7fbbc9,0xbd7bbc48,0x3d623cf1,0x3d80,0x3c95bd75,0xbd0e3d55,0x3d46bd22,0x3cc4bd6d,0xbd223d46,0x3d55bd0e,0xbd753c95,0xbd35bd35,0x3cf13d62,0xbc48bd7b,0xbbc93d7f,
0x3cc43d6d,0xbbc9bd7f,0xbc483d7b,0x3cf1bd62,0x3d800000,0xbd75bc95,0x3d553d0e,0xbd22bd46,0xbd6dbcc4,0x3d463d22,0xbd0ebd55,0x3c953d75,0xbd353d35,0x3d62bcf1,0xbd7b3c48,0x3d7f3bc9,
0x3d35bd35,0xbd753c95,0x3d7b3c48,0xbd46bd22,0x3cc43d6d,0x3bc9bd7f,0xbd0e3d55,0x3d62bcf1,0x3d80,0x3cf1bd62,0xbd553d0e,0x3d7fbbc9,0xbd6dbcc4,0x3d223d46,0xbc48bd7b,0xbc953d75,
0x3d353d35,0xbc95bd75,0xbc483d7b,0x3d22bd46,0xbd6d3cc4,0x3d7f3bc9,0xbd55bd0e,0x3cf13d62,0xbd800000,0x3d623cf1,0xbd0ebd55,0x3bc93d7f,0x3cc4bd6d,0xbd463d22,0x3d7bbc48,0xbd75bc95,
0xbd6dbcc4,0x3cf13d62,0x3c48bd7b,0xbd463d22,0x3d353d35,0xbbc9bd7f,0xbd0e3d55,0x3d75bc95,0xbcc4bd6d,0xbc953d75,0x3d55bd0e,0xbd7fbbc9,0x3d80,0x3d22bd46,0xbd7b3c48,0x3d623cf1,
0xbcc43d6d,0x3d62bcf1,0xbd7bbc48,0x3d223d46,0x3d35bd35,0xbd7f3bc9,0x3d553d0e,0xbc95bd75,0xbd6d3cc4,0x3d753c95,0xbd0ebd55,0xbbc93d7f,0x3d800000,0xbd46bd22,0x3c483d7b,0x3cf1bd62,
0xbd800000,0x3d223d46,0x3c48bd7b,0xbd623cf1,0x3d6d3cc4,0xbc95bd75,0xbd0e3d55,0x3d7fbbc9,0xbd35bd35,0xbbc93d7f,0x3d55bd0e,0xbd75bc95,0x3cc43d6d,0x3cf1bd62,0xbd7b3c48,0x3d463d22,
0x3d80,0x3d46bd22,0xbd7bbc48,0x3cf13d62,0x3cc4bd6d,0xbd753c95,0x3d553d0e,0xbbc9bd7f,0xbd353d35,0x3d7f3bc9,0xbd0ebd55,0xbc953d75,0x3d6dbcc4,0xbd62bcf1,0x3c483d7b,0x3d22bd46,
0xbcc4bd6d,0xbd223d46,0x3d7b3c48,0xbc95bd75,0x3d800000,0xbcf1bd62,0xbd0e3d55,0x3d7f3bc9,0x3d6d3cc4,0xbbc9bd7f,0xbd553d0e,0x3d623cf1,0xbd353d35,0x3d753c95,0xbc48bd7b,0xbd463d22,
0x3d6dbcc4,0xbd46bd22,0xbc483d7b,0x3d75bc95,0x3d80,0x3d62bcf1,0xbd55bd0e,0xbbc93d7f,0xbcc43d6d,0x3d7fbbc9,0xbd0ebd55,0xbcf13d62,0xbd35bd35,0xbc953d75,0x3d7bbc48,0xbd22bd46,
0x3d353d35,0x3cf1bd62,0xbd7bbc48,0x3bc93d7f,0x3d6dbcc4,0xbd22bd46,0xbd0e3d55,0x3d753c95,0xbd800000,0x3c953d75,0x3d55bd0e,0xbd46bd22,0xbcc43d6d,0x3d7f3bc9,0xbc48bd7b,0xbd623cf1,
0x3d35bd35,0xbd62bcf1,0xbc483d7b,0x3d7fbbc9,0xbcc4bd6d,0xbd463d22,0x3d553d0e,0x3c95bd75,0x3d80,0x3d75bc95,0xbd0ebd55,0xbd223d46,0x3d6d3cc4,0x3bc9bd7f,0xbd7b3c48,0x3cf13d62,
0x3cc4bd6d,0xbd75bc95,0xbc483d7b,0x3d7f3bc9,0x3d35bd35,0xbd46bd22,0xbd0e3d55,0x3d623cf1,0x3d6dbcc4,0xbcf1bd62,0xbd553d0e,0x3d223d46,0x3d800000,0xbbc9bd7f,0xbd7b3c48,0x3c953d75,
0x3d6d3cc4,0x3c95bd75,0xbd7bbc48,0xbbc93d7f,0x3d353d35,0x3d22bd46,0xbd55bd0e,0xbcf13d62,0x3cc43d6d,0x3d62bcf1,0xbd0ebd55,0xbd463d22,0x3d80,0x3d7fbbc9,0xbc48bd7b,0xbd753c95,
0xbd800000,0x3d7f3bc9,0xbd7bbc48,0x3d753c95,0xbd6dbcc4,0x3d623cf1,0xbd55bd0e,0x3d463d22,0xbd35bd35,0x3d223d46,0xbd0ebd55,0x3cf13d62,0xbcc4bd6d,0x3c953d75,0xbc48bd7b,0x3bc93d7f,
0x8000bd80,0xbbc93d7f,0x3c48bd7b,0xbc953d75,0x3cc4bd6d,0xbcf13d62,0x3d0ebd55,0xbd223d46,0x3d35bd35,0xbd463d22,0x3d55bd0e,0xbd623cf1,0x3d6dbcc4,0xbd753c95,0x3d7bbc48,0xbd7f3bc9,
0xbcc4bd6d,0x3bc93d7f,0x3c48bd7b,0xbcf13d62,0xbd800000,0x3d753c95,0xbd55bd0e,0x3d223d46,0x3d6d3cc4,0xbd46bd22,0x3d0e3d55,0xbc95bd75,0x3d35bd35,0xbd623cf1,0x3d7bbc48,0xbd7fbbc9,
0xbd6d3cc4,0x3d7fbbc9,0xbd7bbc48,0x3d623cf1,0x80003d80,0x3c95bd75,0xbd0e3d55,0x3d46bd22,0x3cc4bd6d,0xbd223d46,0x3d55bd0e,0xbd753c95,0xbd35bd35,0x3cf13d62,0xbc48bd7b,0xbbc93d7f,
0x3d353d35,0xbc95bd75,0xbc483d7b,0x3d22bd46,0xbd6d3cc4,0x3d7f3bc9,0xbd55bd0e,0x3cf13d62,0xbd800000,0x3d623cf1,0xbd0ebd55,0x3bc93d7f,0x3cc4bd6d,0xbd463d22,0x3d7bbc48,0xbd75bc95,
0xbd353d35,0x3d75bc95,0xbd7bbc48,0x3d463d22,0xbcc4bd6d,0xbbc93d7f,0x3d0ebd55,0xbd623cf1,0x8000bd80,0xbcf13d62,0x3d55bd0e,0xbd7f3bc9,0x3d6d3cc4,0xbd22bd46,0x3c483d7b,0x3c95bd75,
0x3cc4bd6d,0xbd623cf1,0x3d7b3c48,0xbd22bd46,0xbd353d35,0x3d7fbbc9,0xbd55bd0e,0x3c953d75,0x3d6dbcc4,0xbd75bc95,0x3d0e3d55,0x3bc9bd7f,0xbd800000,0x3d463d22,0xbc48bd7b,0xbcf13d62,
0xbd6dbcc4,0x3cf13d62,0x3c48bd7b,0xbd463d22,0x3d353d35,0xbbc9bd7f,0xbd0e3d55,0x3d75bc95,0xbcc4bd6d,0xbc953d75,0x3d55bd0e,0xbd7fbbc9,0x80003d80,0x3d22bd46,0xbd7b3c48,0x3d623cf1,
0x8000bd80,0xbd463d22,0x3d7b3c48,0xbcf1bd62,0xbcc43d6d,0x3d75bc95,0xbd55bd0e,0x3bc93d7f,0x3d35bd35,0xbd7fbbc9,0x3d0e3d55,0x3c95bd75,0xbd6d3cc4,0x3d623cf1,0xbc48bd7b,0xbd223d46,
0xbd800000,0x3d223d46,0x3c48bd7b,0xbd623cf1,0x3d6d3cc4,0xbc95bd75,0xbd0e3d55,0x3d7fbbc9,0xbd35bd35,0xbbc93d7f,0x3d55bd0e,0xbd75bc95,0x3cc43d6d,0x3cf1bd62,0xbd7b3c48,0x3d463d22,
0x3d6dbcc4,0xbd46bd22,0xbc483d7b,0x3d75bc95,0x80003d80,0x3d62bcf1,0xbd55bd0e,0xbbc93d7f,0xbcc43d6d,0x3d7fbbc9,0xbd0ebd55,0xbcf13d62,0xbd35bd35,0xbc953d75,0x3d7bbc48,0xbd22bd46,
0x3cc43d6d,0x3d22bd46,0xbd7bbc48,0x3c953d75,0xbd800000,0x3cf13d62,0x3d0ebd55,0xbd7fbbc9,0xbd6dbcc4,0x3bc93d7f,0x3d55bd0e,0xbd62bcf1,0x3d35bd35,0xbd75bc95,0x3c483d7b,0x3d46bd22,
0xbd353d35,0x3d623cf1,0x3c48bd7b,0xbd7f3bc9,0x3cc43d6d,0x3d46bd22,0xbd55bd0e,0xbc953d75,0x8000bd80,0xbd753c95,0x3d0e3d55,0x3d22bd46,0xbd6dbcc4,0xbbc93d7f,0x3d7bbc48,0xbcf1bd62,
0x3d353d35,0x3cf1bd62,0xbd7bbc48,0x3bc93d7f,0x3d6dbcc4,0xbd22bd46,0xbd0e3d55,0x3d753c95,0xbd800000,0x3c953d75,0x3d55bd0e,0xbd46bd22,0xbcc43d6d,0x3d7f3bc9,0xbc48bd7b,0xbd623cf1,
0x3d6d3cc4,0x3c95bd75,0xbd7bbc48,0xbbc93d7f,0x3d353d35,0x3d22bd46,0xbd55bd0e,0xbcf13d62,0x3cc43d6d,0x3d62bcf1,0xbd0ebd55,0xbd463d22,0x80003d80,0x3d7fbbc9,0xbc48bd7b,0xbd753c95,
0xbcc43d6d,0x3d753c95,0x3c48bd7b,0xbd7fbbc9,0xbd353d35,0x3d463d22,0x3d0ebd55,0xbd62bcf1,0xbd6d3cc4,0x3cf13d62,0x3d55bd0e,0xbd22bd46,0xbd800000,0x3bc93d7f,0x3d7bbc48,0xbc95bd75,
0x3d80,0x3d7f3bc9,0x3c48bd7b,0xbd75bc95,0xbcc43d6d,0x3d623cf1,0x3d0ebd55,0xbd46bd22,0xbd353d35,0x3d223d46,0x3d55bd0e,0xbcf1bd62,0xbd6d3cc4,0x3c953d75,0x3d7bbc48,0xbbc9bd7f,
0xbd800000,0xbbc93d7f,0x3d7b3c48,0x3c95bd75,0xbd6dbcc4,0xbcf13d62,0x3d553d0e,0x3d22bd46,0xbd35bd35,0xbd463d22,0x3d0e3d55,0x3d62bcf1,0xbcc4bd6d,0xbd753c95,0x3c483d7b,0x3d7fbbc9,
0xbd6d3cc4,0x3bc93d7f,0x3d7b3c48,0x3cf1bd62,0x3d80,0x3d753c95,0x3d0ebd55,0xbd22bd46,0x3cc4bd6d,0xbd46bd22,0xbd553d0e,0x3c953d75,0xbd35bd35,0xbd623cf1,0x3c483d7b,0x3d7f3bc9,
0x3cc43d6d,0x3d7fbbc9,0x3c48bd7b,0xbd62bcf1,0x3d800000,0x3c95bd75,0xbd55bd0e,0xbd463d22,0xbd6dbcc4,0xbd223d46,0x3d0e3d55,0x3d75bc95,0xbd353d35,0x3cf13d62,0x3d7bbc48,0x3bc9bd7f,
0x3d35bd35,0xbc95bd75,0xbd7bbc48,0xbd223d46,0x3cc43d6d,0x3d7f3bc9,0x3d0ebd55,0xbcf1bd62,0x3d80,0x3d623cf1,0x3d55bd0e,0xbbc9bd7f,0xbd6dbcc4,0xbd463d22,0x3c483d7b,0x3d753c95,
0x3d353d35,0x3d75bc95,0x3c48bd7b,0xbd46bd22,0xbd6d3cc4,0xbbc93d7f,0x3d553d0e,0x3d62bcf1,0xbd800000,0xbcf13d62,0x3d0e3d55,0x3d7fbbc9,0x3cc4bd6d,0xbd22bd46,0xbd7b3c48,0xbc953d75,
0xbd6dbcc4,0xbd623cf1,0xbc483d7b,0x3d223d46,0x3d353d35,0x3d7fbbc9,0x3d0ebd55,0xbc95bd75,0xbcc4bd6d,0xbd75bc95,0xbd553d0e,0xbbc93d7f,0x3d80,0x3d463d22,0x3d7bbc48,0x3cf1bd62,
0xbcc43d6d,0x3cf13d62,0x3d7b3c48,0x3d46bd22,0x3d35bd35,0xbbc9bd7f,0xbd55bd0e,0xbd753c95,0xbd6d3cc4,0xbc953d75,0x3d0e3d55,0x3d7f3bc9,0x3d800000,0x3d22bd46,0xbc48bd7b,0xbd62bcf1,
0xbd800000,0xbd463d22,0xbc483d7b,0x3cf13d62,0x3d6d3cc4,0x3d75bc95,0x3d0ebd55,0xbbc9bd7f,0xbd35bd35,0xbd7fbbc9,0xbd553d0e,0xbc953d75,0x3cc43d6d,0x3d623cf1,0x3d7bbc48,0x3d22bd46,
0x3d80,0x3d223d46,0x3d7b3c48,0x3d62bcf1,0x3cc4bd6d,0xbc95bd75,0xbd55bd0e,0xbd7f3bc9,0xbd353d35,0xbbc93d7f,0x3d0e3d55,0x3d753c95,0x3d6dbcc4,0x3cf1bd62,0xbc48bd7b,0xbd46bd22,
0xbcc4bd6d,0xbd46bd22,0xbd7bbc48,0xbd753c95,0x3d800000,0x3d62bcf1,0x3d0ebd55,0x3bc9bd7f,0x3d6d3cc4,0x3d7fbbc9,0x3d55bd0e,0x3cf1bd62,0xbd353d35,0xbc953d75,0x3c483d7b,0x3d223d46,
0x3d6dbcc4,0x3d22bd46,0x3c48bd7b,0xbc95bd75,0x3d80,0x3cf13d62,0x3d553d0e,0x3d7f3bc9,0xbcc43d6d,0x3bc93d7f,0x3d0e3d55,0x3d623cf1,0xbd35bd35,0xbd75bc95,0xbd7b3c48,0xbd463d22,
0x3d353d35,0x3d623cf1,0x3d7b3c48,0x3d7fbbc9,0x3d6dbcc4,0x3d46bd22,0x3d0ebd55,0x3c95bd75,0xbd800000,0xbd753c95,0xbd553d0e,0xbd223d46,0xbcc43d6d,0xbbc93d7f,0x3c483d7b,0x3cf13d62,
0x3d35bd35,0x3cf1bd62,0x3c48bd7b,0xbbc9bd7f,0xbcc4bd6d,0xbd22bd46,0xbd55bd0e,0xbd75bc95,0x3d80,0x3c953d75,0x3d0e3d55,0x3d463d22,0x3d6d3cc4,0x3d7f3bc9,0x3d7bbc48,0x3d62bcf1,
0x3cc4bd6d,0x3c95bd75,0x3c48bd7b,0x3bc9bd7f,0x3d35bd35,0x3d22bd46,0x3d0ebd55,0x3cf1bd62,0x3d6dbcc4,0x3d62bcf1,0x3d55bd0e,0x3d46bd22,0x3d800000,0x3d7fbbc9,0x3d7bbc48,0x3d75bc95,
0x3d6d3cc4,0x3d753c95,0x3d7b3c48,0x3d7f3bc9,0x3d353d35,0x3d463d22,0x3d553d0e,0x3d623cf1,0x3cc43d6d,0x3cf13d62,0x3d0e3d55,0x3d223d46,0x3d80,0x3bc93d7f,0x3c483d7b,0x3c953d75,
0xbd800000,0xbbc93d7f,0x3d7b3c48,0x3c95bd75,0xbd6dbcc4,0xbcf13d62,0x3d553d0e,0x3d22bd46,0xbd35bd35,0xbd463d22,0x3d0e3d55,0x3d62bcf1,0xbcc4bd6d,0xbd753c95,0x3c483d7b,0x3d7fbbc9,
0x8000bd80,0xbd7fbbc9,0xbc483d7b,0x3d753c95,0x3cc4bd6d,0xbd62bcf1,0xbd0e3d55,0x3d463d22,0x3d35bd35,0xbd22bd46,0xbd553d0e,0x3cf13d62,0x3d6dbcc4,0xbc95bd75,0xbd7b3c48,0x3bc93d7f,
0xbcc4bd6d,0xbd7f3bc9,0xbc483d7b,0x3d623cf1,0xbd800000,0xbc953d75,0x3d553d0e,0x3d46bd22,0x3d6d3cc4,0x3d22bd46,0xbd0ebd55,0xbd753c95,0x3d35bd35,0xbcf1bd62,0xbd7b3c48,0xbbc93d7f,
0xbd6d3cc4,0x3bc93d7f,0x3d7b3c48,0x3cf1bd62,0x80003d80,0x3d753c95,0x3d0ebd55,0xbd22bd46,0x3cc4bd6d,0xbd46bd22,0xbd553d0e,0x3c953d75,0xbd35bd35,0xbd623cf1,0x3c483d7b,0x3d7f3bc9,
0x3d353d35,0x3d75bc95,0x3c48bd7b,0xbd46bd22,0xbd6d3cc4,0xbbc93d7f,0x3d553d0e,0x3d62bcf1,0xbd800000,0xbcf13d62,0x3d0e3d55,0x3d7fbbc9,0x3cc4bd6d,0xbd22bd46,0xbd7b3c48,0xbc953d75,
0xbd353d35,0x3c953d75,0x3d7b3c48,0x3d22bd46,0xbcc4bd6d,0xbd7fbbc9,0xbd0e3d55,0x3cf13d62,0x8000bd80,0xbd62bcf1,0xbd553d0e,0x3bc93d7f,0x3d6d3cc4,0x3d46bd22,0xbc48bd7b,0xbd75bc95,
0x3cc4bd6d,0xbcf1bd62,0xbd7bbc48,0xbd463d22,0xbd353d35,0x3bc93d7f,0x3d553d0e,0x3d75bc95,0x3d6dbcc4,0x3c95bd75,0xbd0ebd55,0xbd7fbbc9,0xbd800000,0xbd223d46,0x3c483d7b,0x3d623cf1,
0xbd6dbcc4,0xbd623cf1,0xbc483d7b,0x3d223d46,0x3d353d35,0x3d7fbbc9,0x3d0ebd55,0xbc95bd75,0xbcc4bd6d,0xbd75bc95,0xbd553d0e,0xbbc93d7f,0x80003d80,0x3d463d22,0x3d7bbc48,0x3cf1bd62,
0x8000bd80,0xbd22bd46,0xbd7bbc48,0xbd623cf1,0xbcc43d6d,0x3c953d75,0x3d553d0e,0x3d7fbbc9,0x3d35bd35,0x3bc9bd7f,0xbd0ebd55,0xbd75bc95,0xbd6d3cc4,0xbcf13d62,0x3c483d7b,0x3d463d22,
0xbd800000,0xbd463d22,0xbc483d7b,0x3cf13d62,0x3d6d3cc4,0x3d75bc95,0x3d0ebd55,0xbbc9bd7f,0xbd35bd35,0xbd7fbbc9,0xbd553d0e,0xbc953d75,0x3cc43d6d,0x3d623cf1,0x3d7bbc48,0x3d22bd46,
0x3d6dbcc4,0x3d22bd46,0x3c48bd7b,0xbc95bd75,0x80003d80,0x3cf13d62,0x3d553d0e,0x3d7f3bc9,0xbcc43d6d,0x3bc93d7f,0x3d0e3d55,0x3d623cf1,0xbd35bd35,0xbd75bc95,0xbd7b3c48,0xbd463d22,
0x3cc43d6d,0x3d463d22,0x3d7b3c48,0x3d75bc95,0xbd800000,0xbd623cf1,0xbd0e3d55,0xbbc93d7f,0xbd6dbcc4,0xbd7f3bc9,0xbd553d0e,0xbcf13d62,0x3d35bd35,0x3c95bd75,0xbc48bd7b,0xbd22bd46,
0xbd353d35,0xbcf13d62,0xbc483d7b,0x3bc93d7f,0x3cc43d6d,0x3d223d46,0x3d553d0e,0x3d753c95,0x8000bd80,0xbc95bd75,0xbd0ebd55,0xbd46bd22,0xbd6dbcc4,0xbd7fbbc9,0xbd7b3c48,0xbd623cf1,
0x3d353d35,0x3d623cf1,0x3d7b3c48,0x3d7fbbc9,0x3d6dbcc4,0x3d46bd22,0x3d0ebd55,0x3c95bd75,0xbd800000,0xbd753c95,0xbd553d0e,0xbd223d46,0xbcc43d6d,0xbbc93d7f,0x3c483d7b,0x3cf13d62,
0x3d6d3cc4,0x3d753c95,0x3d7b3c48,0x3d7f3bc9,0x3d353d35,0x3d463d22,0x3d553d0e,0x3d623cf1,0x3cc43d6d,0x3cf13d62,0x3d0e3d55,0x3d223d46,0x80003d80,0x3bc93d7f,0x3c483d7b,0x3c953d75,
0xbcc43d6d,0xbc953d75,0xbc483d7b,0xbbc93d7f,0xbd353d35,0xbd223d46,0xbd0e3d55,0xbcf13d62,0xbd6d3cc4,0xbd623cf1,0xbd553d0e,0xbd463d22,0xbd800000,0xbd7f3bc9,0xbd7b3c48,0xbd753c95,
0x3d80,0xbc163d7d,0xbc953d75,0xbcdb3d67,0xbd0e3d55,0xbd2c3d3e,0xbd463d22,0xbd5c3d04,0xbd6d3cc4,0xbd783c79,0xbd7f3bc9,0xbd80bb49,0xbd7bbc48,0xbd71bcac,0xbd62bcf1,0xbd4ebd18,
0xbd35bd35,0xbd18bd4e,0xbcf1bd62,0xbcacbd71,0xbc48bd7b,0xbb49bd80,0x3bc9bd7f,0x3c79bd78,0x3cc4bd6d,0x3d04bd5c,0x3d22bd46,0x3d3ebd2c,0x3d55bd0e,0x3d67bcdb,0x3d75bc95,0x3d7dbc16,
0xbd7b3c48,0xbd7dbc16,0xbd62bcf1,0xbd2cbd3e,0x3d80,0xbcac3d71,0xbd223d46,0xbd5c3d04,0x3d55bd0e,0x3d78bc79,0x3d7f3bc9,0x3d673cdb,0xbcc4bd6d,0xbb49bd80,0x3c95bd75,0x3d18bd4e,
0xbd0e3d55,0xbd4e3d18,0xbd753c95,0xbd80bb49,0x3d353d35,0x3cdb3d67,0x3bc93d7f,0xbc793d78,0x3c48bd7b,0x3d04bd5c,0x3d46bd22,0x3d71bcac,0xbd6dbcc4,0xbd3ebd2c,0xbcf1bd62,0xbc16bd7d,
0x3d6dbcc4,0x3d7d3c16,0x3d463d22,0x3cac3d71,0xbc483d7b,0xbd2c3d3e,0xbd753c95,0xbd78bc79,0x3d80,0xbd043d5c,0xbd623cf1,0xbd80bb49,0xbd55bd0e,0xbcdbbd67,0x3bc9bd7f,0x3d18bd4e,
0xbcc43d6d,0xbd4e3d18,0xbd7f3bc9,0xbd67bcdb,0xbd0ebd55,0xbb49bd80,0x3cf1bd62,0x3d5cbd04,0xbd35bd35,0xbc79bd78,0x3c95bd75,0x3d3ebd2c,0x3d7bbc48,0x3d713cac,0x3d223d46,0x3c163d7d,
0xbd0ebd55,0x3c16bd7d,0x3d46bd22,0x3d803b49,0x3cc43d6d,0xbcac3d71,0xbd623cf1,0xbd78bc79,0xbc48bd7b,0x3d04bd5c,0x3d75bc95,0x3d673cdb,0x3d80,0xbd2c3d3e,0xbd7f3bc9,0xbd4ebd18,
0xbd7bbc48,0xbd18bd4e,0x3bc9bd7f,0x3d3ebd2c,0x3d6d3cc4,0x3cdb3d67,0xbc953d75,0xbd5c3d04,0xbd55bd0e,0xbc79bd78,0x3cf1bd62,0x3d71bcac,0x3d353d35,0x3b493d80,0xbd223d46,0xbd7d3c16,
0xbd35bd35,0x3c16bd7d,0x3d62bcf1,0x3d673cdb,0x3c483d7b,0xbd2c3d3e,0xbd7fbbc9,0xbd04bd5c,0x3cc4bd6d,0x3d78bc79,0x3d463d22,0xbb493d80,0xbd553d0e,0xbd71bcac,0xbc95bd75,0x3d18bd4e,
0x3d80,0xbd4e3d18,0xbd75bc95,0xbcacbd71,0x3d0ebd55,0x3d80bb49,0x3d223d46,0xbc793d78,0xbd6d3cc4,0xbd5cbd04,0xbbc9bd7f,0x3d3ebd2c,0x3d7b3c48,0x3cdb3d67,0xbcf13d62,0xbd7d3c16,
0x3d0ebd55,0x3d7d3c16,0x3c953d75,0xbd3e3d2c,0x3d353d35,0xbcac3d71,0xbd7f3bc9,0xbd04bd5c,0xbc483d7b,0xbd783c79,0xbd22bd46,0x3cdbbd67,0xbd6dbcc4,0xbb49bd80,0x3d62bcf1,0x3d4e3d18,
0x3d7bbc48,0x3d183d4e,0xbcf13d62,0xbd80bb49,0x3d80,0xbd673cdb,0xbd46bd22,0x3c79bd78,0xbd553d0e,0xbd5cbd04,0x3bc9bd7f,0x3d71bcac,0xbcc4bd6d,0x3d2cbd3e,0x3d753c95,0x3c163d7d,
0xbcc43d6d,0xbd7dbc16,0xbbc9bd7f,0x3d71bcac,0x3d0e3d55,0xbd2c3d3e,0xbd62bcf1,0x3c79bd78,0xbd35bd35,0x3d04bd5c,0x3d753c95,0xbb493d80,0xbd7b3c48,0xbcdbbd67,0x3d46bd22,0x3d4e3d18,
0x3d6dbcc4,0x3d183d4e,0xbd223d46,0xbd67bcdb,0x3c48bd7b,0x3d80bb49,0x3c953d75,0xbd5c3d04,0x3d80,0xbd783c79,0xbcf1bd62,0x3d3ebd2c,0x3d553d0e,0xbcac3d71,0xbd7fbbc9,0xbc16bd7d,
0x3d7b3c48,0xbc163d7d,0xbd7fbbc9,0x3b49bd80,0x3d6d3cc4,0xbcac3d71,0xbd75bc95,0x3c79bd78,0x3d553d0e,0xbd043d5c,0xbd62bcf1,0x3cdbbd67,0x3d353d35,0xbd2c3d3e,0xbd46bd22,0x3d18bd4e,
0x3d0e3d55,0xbd4e3d18,0xbd22bd46,0x3d3ebd2c,0x3cc43d6d,0xbd673cdb,0xbcf1bd62,0x3d5cbd04,0x3c483d7b,0xbd783c79,0xbc95bd75,0x3d71bcac,0x3d80,0xbd803b49,0xbbc9bd7f,0x3d7dbc16,
0xbd800000,0xbd7dbc16,0xbd75bc95,0xbd67bcdb,0xbd55bd0e,0xbd3ebd2c,0xbd22bd46,0xbd04bd5c,0xbcc4bd6d,0xbc79bd78,0xbbc9bd7f,0x3b49bd80,0x3c48bd7b,0x3cacbd71,0x3cf1bd62,0x3d18bd4e,
0x3d35bd35,0x3d4ebd18,0x3d62bcf1,0x3d71bcac,0x3d7bbc48,0x3d80bb49,0x3d7f3bc9,0x3d783c79,0x3d6d3cc4,0x3d5c3d04,0x3d463d22,0x3d2c3d3e,0x3d0e3d55,0x3cdb3d67,0x3c953d75,0x3c163d7d,
0xbc48bd7b,0x3c16bd7d,0x3cf1bd62,0x3d3ebd2c,0xbd800000,0xbd71bcac,0xbd46bd22,0xbd04bd5c,0x3d0e3d55,0x3c793d78,0xbbc93d7f,0xbcdb3d67,0x3d6dbcc4,0x3d80bb49,0x3d753c95,0x3d4e3d18,
0xbd55bd0e,0xbd18bd4e,0xbc95bd75,0x3b49bd80,0xbd353d35,0xbd673cdb,0xbd7f3bc9,0xbd78bc79,0x3d7b3c48,0x3d5c3d04,0x3d223d46,0x3cac3d71,0x3cc4bd6d,0x3d2cbd3e,0x3d62bcf1,0x3d7dbc16,
0x3cc43d6d,0xbc163d7d,0xbd223d46,0xbd713cac,0xbd7bbc48,0xbd3ebd2c,0xbc95bd75,0x3c79bd78,0xbd800000,0xbd5cbd04,0xbcf1bd62,0x3b49bd80,0x3d0ebd55,0x3d67bcdb,0x3d7f3bc9,0x3d4e3d18,
0xbd6dbcc4,0xbd18bd4e,0xbbc9bd7f,0x3cdbbd67,0x3d55bd0e,0x3d80bb49,0x3d623cf1,0x3d043d5c,0x3d35bd35,0x3d78bc79,0x3d753c95,0x3d2c3d3e,0x3c483d7b,0xbcac3d71,0xbd463d22,0xbd7d3c16,
0x3d55bd0e,0x3d7d3c16,0x3d223d46,0xbb493d80,0xbd6d3cc4,0xbd71bcac,0xbcf1bd62,0x3c79bd78,0x3d7bbc48,0x3d5c3d04,0x3c953d75,0xbcdb3d67,0xbd800000,0xbd3ebd2c,0xbbc9bd7f,0x3d18bd4e,
0x3c48bd7b,0x3d4ebd18,0x3d7f3bc9,0x3d2c3d3e,0xbcc43d6d,0xbd673cdb,0xbd75bc95,0xbd04bd5c,0x3d0ebd55,0x3d78bc79,0x3d623cf1,0x3cac3d71,0xbd353d35,0xbd803b49,0xbd46bd22,0xbc16bd7d,
0x3d35bd35,0x3d7d3c16,0x3cf13d62,0xbcdb3d67,0xbd7b3c48,0xbd3ebd2c,0x3bc9bd7f,0x3d5cbd04,0x3d6d3cc4,0x3c793d78,0xbd223d46,0xbd80bb49,0xbd0ebd55,0x3cacbd71,0x3d75bc95,0x3d4e3d18,
0xbd800000,0xbd18bd4e,0x3c95bd75,0x3d71bcac,0x3d553d0e,0x3b493d80,0xbd463d22,0xbd78bc79,0xbcc4bd6d,0x3d04bd5c,0x3d7fbbc9,0x3d2c3d3e,0xbc483d7b,0xbd673cdb,0xbd62bcf1,0xbc16bd7d,
0x3d553d0e,0xbc163d7d,0xbd753c95,0xbd2cbd3e,0xbd353d35,0xbd71bcac,0xbbc9bd7f,0x3d5cbd04,0xbd7bbc48,0xbc79bd78,0x3d46bd22,0x3d673cdb,0x3cc4bd6d,0x3d80bb49,0x3cf13d62,0xbd183d4e,
0x3c483d7b,0xbd4e3d18,0xbd62bcf1,0x3b49bd80,0xbd800000,0xbcdbbd67,0x3d22bd46,0x3d783c79,0xbd0ebd55,0x3d04bd5c,0x3d7f3bc9,0x3cac3d71,0x3d6dbcc4,0x3d3e3d2c,0xbc953d75,0xbd7d3c16,
0xbd6dbcc4,0x3c16bd7d,0x3d7fbbc9,0x3cac3d71,0xbd553d0e,0xbd3ebd2c,0x3cf1bd62,0x3d783c79,0x3d35bd35,0x3d5c3d04,0xbc953d75,0xbd80bb49,0xbc48bd7b,0x3d67bcdb,0x3d223d46,0xbd183d4e,
0x3cc43d6d,0xbd4e3d18,0xbd46bd22,0x3cdbbd67,0x3d7b3c48,0x3b493d80,0xbd753c95,0xbd04bd5c,0xbd800000,0xbc79bd78,0x3d62bcf1,0x3d2c3d3e,0xbd0e3d55,0xbd71bcac,0x3bc9bd7f,0x3d7dbc16,
0xbc483d7b,0xbd7dbc16,0x3bc9bd7f,0x3d803b49,0xbcc43d6d,0xbd71bcac,0x3c95bd75,0x3d783c79,0xbd0e3d55,0xbd5cbd04,0x3cf1bd62,0x3d673cdb,0xbd353d35,0xbd3ebd2c,0x3d22bd46,0x3d4e3d18,
0xbd553d0e,0xbd18bd4e,0x3d46bd22,0x3d2c3d3e,0xbd6d3cc4,0xbcdbbd67,0x3d62bcf1,0x3d043d5c,0xbd7b3c48,0xbc79bd78,0x3d75bc95,0x3cac3d71,0xbd800000,0xbb49bd80,0x3d7fbbc9,0x3c163d7d,
0x3d80,0xbd7dbc16,0x3c95bd75,0x3d673cdb,0xbd0e3d55,0xbd3ebd2c,0x3d46bd22,0x3d043d5c,0xbd6d3cc4,0xbc79bd78,0x3d7fbbc9,0xbb493d80,0xbd7bbc48,0x3cacbd71,0x3d623cf1,0xbd183d4e,
0xbd35bd35,0x3d4ebd18,0x3cf13d62,0xbd713cac,0xbc48bd7b,0x3d80bb49,0xbbc93d7f,0xbd78bc79,0x3cc4bd6d,0x3d5c3d04,0xbd223d46,0xbd2cbd3e,0x3d55bd0e,0x3cdb3d67,0xbd753c95,0xbc16bd7d,
0xbd7b3c48,0x3c16bd7d,0x3d623cf1,0xbd3e3d2c,0x3d80,0xbd71bcac,0x3d22bd46,0x3d043d5c,0x3d55bd0e,0x3c793d78,0xbd7fbbc9,0x3cdbbd67,0xbcc4bd6d,0x3d80bb49,0xbc953d75,0xbd4ebd18,
0xbd0e3d55,0xbd18bd4e,0x3d75bc95,0xbb493d80,0x3d353d35,0xbd673cdb,0xbbc9bd7f,0x3d783c79,0x3c48bd7b,0x3d5c3d04,0xbd463d22,0xbcacbd71,0xbd6dbcc4,0x3d2cbd3e,0x3cf13d62,0xbd7d3c16,
0x3d6dbcc4,0xbc163d7d,0xbd46bd22,0x3d71bcac,0xbc483d7b,0xbd3ebd2c,0x3d75bc95,0xbc793d78,0x3d80,0xbd5cbd04,0x3d62bcf1,0xbb493d80,0xbd55bd0e,0x3d67bcdb,0xbbc93d7f,0xbd4ebd18,
0xbcc43d6d,0xbd18bd4e,0x3d7fbbc9,0xbcdb3d67,0xbd0ebd55,0x3d80bb49,0xbcf13d62,0xbd04bd5c,0xbd35bd35,0x3d78bc79,0xbc953d75,0xbd2cbd3e,0x3d7bbc48,0xbcac3d71,0xbd22bd46,0x3d7dbc16,
0xbd0ebd55,0x3d7d3c16,0xbd463d22,0x3b49bd80,0x3cc43d6d,0xbd71bcac,0x3d62bcf1,0xbc793d78,0xbc48bd7b,0x3d5c3d04,0xbd753c95,0x3cdbbd67,0x3d80,0xbd3ebd2c,0x3d7fbbc9,0xbd183d4e,
0xbd7bbc48,0x3d4ebd18,0xbbc93d7f,0xbd2cbd3e,0x3d6d3cc4,0xbd673cdb,0x3c95bd75,0x3d043d5c,0xbd55bd0e,0x3d78bc79,0xbcf13d62,0xbcacbd71,0x3d353d35,0xbd803b49,0x3d22bd46,0x3c163d7d,
0xbd35bd35,0x3d7d3c16,0xbd623cf1,0x3cdbbd67,0x3c483d7b,0xbd3ebd2c,0x3d7f3bc9,0xbd5c3d04,0x3cc4bd6d,0x3c793d78,0xbd46bd22,0x3d803b49,0xbd553d0e,0x3cacbd71,0x3c953d75,0xbd4ebd18,
0x3d80,0xbd18bd4e,0x3d753c95,0xbd713cac,0x3d0ebd55,0x3b493d80,0xbd22bd46,0x3d783c79,0xbd6d3cc4,0x3d04bd5c,0x3bc93d7f,0xbd2cbd3e,0x3d7b3c48,0xbd673cdb,0x3cf1bd62,0x3c163d7d,
0x3d0ebd55,0xbc163d7d,0xbc95bd75,0x3d2c3d3e,0x3d353d35,0xbd71bcac,0x3d7fbbc9,0xbd5c3d04,0xbc483d7b,0xbc79bd78,0x3d223d46,0xbd67bcdb,0xbd6dbcc4,0x3d80bb49,0xbd623cf1,0x3d18bd4e,
0x3d7bbc48,0xbd4e3d18,0x3cf1bd62,0xbb493d80,0x3d80,0xbcdbbd67,0x3d463d22,0xbd78bc79,0xbd553d0e,0x3d04bd5c,0xbbc93d7f,0xbcacbd71,0xbcc4bd6d,0x3d3e3d2c,0xbd75bc95,0x3d7dbc16,
0xbcc43d6d,0x3c16bd7d,0x3bc93d7f,0xbcacbd71,0x3d0e3d55,0xbd3ebd2c,0x3d623cf1,0xbd78bc79,0xbd35bd35,0x3d5c3d04,0xbd75bc95,0x3d803b49,0xbd7b3c48,0x3d67bcdb,0xbd463d22,0x3d18bd4e,
0x3d6dbcc4,0xbd4e3d18,0x3d22bd46,0xbcdb3d67,0x3c48bd7b,0x3b493d80,0xbc95bd75,0x3d043d5c,0x3d80,0xbc79bd78,0x3cf13d62,0xbd2cbd3e,0x3d553d0e,0xbd71bcac,0x3d7f3bc9,0xbd7d3c16,
0x3d7b3c48,0xbd7dbc16,0x3d7f3bc9,0xbd80bb49,0x3d6d3cc4,0xbd71bcac,0x3d753c95,0xbd78bc79,0x3d553d0e,0xbd5cbd04,0x3d623cf1,0xbd67bcdb,0x3d353d35,0xbd3ebd2c,0x3d463d22,0xbd4ebd18,
0x3d0e3d55,0xbd18bd4e,0x3d223d46,0xbd2cbd3e,0x3cc43d6d,0xbcdbbd67,0x3cf13d62,0xbd04bd5c,0x3c483d7b,0xbc79bd78,0x3c953d75,0xbcacbd71,0x3d80,0xbb49bd80,0x3bc93d7f,0xbc16bd7d,
0xbd800000,0x3c16bd7d,0x3d753c95,0xbcdb3d67,0xbd55bd0e,0x3d2cbd3e,0x3d223d46,0xbd5c3d04,0xbcc4bd6d,0x3d78bc79,0x3bc93d7f,0xbd80bb49,0x3c48bd7b,0x3d713cac,0xbcf13d62,0xbd4ebd18,
0x3d35bd35,0x3d183d4e,0xbd623cf1,0xbcacbd71,0x3d7bbc48,0x3b493d80,0xbd7fbbc9,0x3c79bd78,0x3d6d3cc4,0xbd043d5c,0xbd46bd22,0x3d3ebd2c,0x3d0e3d55,0xbd673cdb,0xbc95bd75,0x3d7dbc16,
0xbc48bd7b,0x3d7d3c16,0xbcf13d62,0xbd2cbd3e,0xbd800000,0x3cacbd71,0x3d463d22,0xbd5c3d04,0x3d0e3d55,0xbd783c79,0x3bc9bd7f,0x3d673cdb,0x3d6dbcc4,0x3b493d80,0xbd75bc95,0x3d18bd4e,
0xbd55bd0e,0x3d4ebd18,0x3c953d75,0xbd80bb49,0xbd353d35,0xbcdbbd67,0x3d7fbbc9,0xbc793d78,0x3d7b3c48,0xbd043d5c,0xbd22bd46,0x3d71bcac,0x3cc4bd6d,0x3d3e3d2c,0xbd623cf1,0xbc16bd7d,
0x3cc43d6d,0xbd7dbc16,0x3d22bd46,0x3cac3d71,0xbd7bbc48,0x3d2cbd3e,0x3c953d75,0xbd78bc79,0xbd800000,0x3d04bd5c,0x3cf13d62,0xbd80bb49,0x3d0ebd55,0x3cdb3d67,0xbd7fbbc9,0x3d18bd4e,
0xbd6dbcc4,0x3d4ebd18,0x3bc93d7f,0xbd67bcdb,0x3d55bd0e,0x3b493d80,0xbd62bcf1,0x3d5cbd04,0x3d35bd35,0x3c793d78,0xbd75bc95,0x3d3ebd2c,0x3c483d7b,0xbd71bcac,0x3d46bd22,0x3c163d7d,
0x3d55bd0e,0xbc163d7d,0xbd22bd46,0x3d803b49,0xbd6d3cc4,0x3cacbd71,0x3cf13d62,0xbd78bc79,0x3d7bbc48,0xbd043d5c,0xbc95bd75,0x3d673cdb,0xbd800000,0x3d2cbd3e,0x3bc93d7f,0xbd4ebd18,
0x3c48bd7b,0x3d183d4e,0xbd7fbbc9,0x3d3ebd2c,0xbcc43d6d,0xbcdbbd67,0x3d753c95,0xbd5c3d04,0x3d0ebd55,0x3c793d78,0xbd62bcf1,0x3d71bcac,0xbd353d35,0xbb49bd80,0x3d463d22,0xbd7d3c16,
0x3d35bd35,0xbc163d7d,0xbcf1bd62,0x3d673cdb,0xbd7b3c48,0x3d2cbd3e,0xbbc93d7f,0xbd04bd5c,0x3d6d3cc4,0xbd783c79,0x3d22bd46,0xbb493d80,0xbd0ebd55,0x3d713cac,0xbd753c95,0x3d18bd4e,
0xbd800000,0x3d4ebd18,0xbc953d75,0xbcacbd71,0x3d553d0e,0xbd803b49,0x3d46bd22,0xbc793d78,0xbcc4bd6d,0x3d5c3d04,0xbd7f3bc9,0x3d3ebd2c,0xbc483d7b,0xbcdbbd67,0x3d623cf1,0xbd7d3c16,
0x3d553d0e,0xbd7dbc16,0x3d75bc95,0xbd3e3d2c,0xbd353d35,0x3cacbd71,0x3bc93d7f,0xbd04bd5c,0xbd7bbc48,0x3d78bc79,0xbd463d22,0x3cdbbd67,0x3cc4bd6d,0x3b493d80,0xbcf1bd62,0x3d4e3d18,
0x3c483d7b,0xbd18bd4e,0x3d623cf1,0xbd80bb49,0xbd800000,0x3d67bcdb,0xbd223d46,0x3c79bd78,0xbd0ebd55,0x3d5c3d04,0xbd7fbbc9,0x3d71bcac,0x3d6dbcc4,0xbd2c3d3e,0x3c95bd75,0x3c163d7d,
0xbd6dbcc4,0x3d7d3c16,0xbd7f3bc9,0x3d71bcac,0xbd553d0e,0x3d2cbd3e,0xbcf13d62,0x3c79bd78,0x3d35bd35,0xbd043d5c,0x3c95bd75,0xbb493d80,0xbc48bd7b,0x3cdb3d67,0xbd22bd46,0x3d4e3d18,
0x3cc43d6d,0xbd18bd4e,0x3d463d22,0xbd67bcdb,0x3d7b3c48,0xbd803b49,0x3d75bc95,0xbd5c3d04,0xbd800000,0x3d78bc79,0xbd623cf1,0x3d3ebd2c,0xbd0e3d55,0x3cacbd71,0xbbc93d7f,0xbc16bd7d,
0xbc483d7b,0x3c16bd7d,0xbbc93d7f,0x3b49bd80,0xbcc43d6d,0x3cacbd71,0xbc953d75,0x3c79bd78,0xbd0e3d55,0x3d04bd5c,0xbcf13d62,0x3cdbbd67,0xbd353d35,0x3d2cbd3e,0xbd223d46,0x3d18bd4e,
0xbd553d0e,0x3d4ebd18,0xbd463d22,0x3d3ebd2c,0xbd6d3cc4,0x3d67bcdb,0xbd623cf1,0x3d5cbd04,0xbd7b3c48,0x3d78bc79,0xbd753c95,0x3d71bcac,0xbd800000,0x3d80bb49,0xbd7f3bc9,0x3d7dbc16,
0x3d80,0x3c16bd7d,0xbc953d75,0x3cdbbd67,0xbd0e3d55,0x3d2cbd3e,0xbd463d22,0x3d5cbd04,0xbd6d3cc4,0x3d78bc79,0xbd7f3bc9,0x3d803b49,0xbd7bbc48,0x3d713cac,0xbd62bcf1,0x3d4e3d18,
0xbd35bd35,0x3d183d4e,0xbcf1bd62,0x3cac3d71,0xbc48bd7b,0x3b493d80,0x3bc9bd7f,0xbc793d78,0x3cc4bd6d,0xbd043d5c,0x3d22bd46,0xbd3e3d2c,0x3d55bd0e,0xbd673cdb,0x3d75bc95,0xbd7d3c16,
0xbd7b3c48,0x3d7d3c16,0xbd62bcf1,0x3d2c3d3e,0x3d80,0x3cacbd71,0xbd223d46,0x3d5cbd04,0x3d55bd0e,0xbd783c79,0x3d7f3bc9,0xbd67bcdb,0xbcc4bd6d,0x3b493d80,0x3c95bd75,0xbd183d4e,
0xbd0e3d55,0x3d4ebd18,0xbd753c95,0x3d803b49,0x3d353d35,0xbcdbbd67,0x3bc93d7f,0x3c79bd78,0x3c48bd7b,0xbd043d5c,0x3d46bd22,0xbd713cac,0xbd6dbcc4,0x3d3e3d2c,0xbcf1bd62,0x3c163d7d,
0x3d6dbcc4,0xbd7dbc16,0x3d463d22,0xbcacbd71,0xbc483d7b,0x3d2cbd3e,0xbd753c95,0x3d783c79,0x3d80,0x3d04bd5c,0xbd623cf1,0x3d803b49,0xbd55bd0e,0x3cdb3d67,0x3bc9bd7f,0xbd183d4e,
0xbcc43d6d,0x3d4ebd18,0xbd7f3bc9,0x3d673cdb,0xbd0ebd55,0x3b493d80,0x3cf1bd62,0xbd5c3d04,0xbd35bd35,0x3c793d78,0x3c95bd75,0xbd3e3d2c,0x3d7bbc48,0xbd71bcac,0x3d223d46,0xbc16bd7d,
0xbd0ebd55,0xbc163d7d,0x3d46bd22,0xbd80bb49,0x3cc43d6d,0x3cacbd71,0xbd623cf1,0x3d783c79,0xbc48bd7b,0xbd043d5c,0x3d75bc95,0xbd67bcdb,0x3d80,0x3d2cbd3e,0xbd7f3bc9,0x3d4e3d18,
0xbd7bbc48,0x3d183d4e,0x3bc9bd7f,0xbd3e3d2c,0x3d6d3cc4,0xbcdbbd67,0xbc953d75,0x3d5cbd04,0xbd55bd0e,0x3c793d78,0x3cf1bd62,0xbd713cac,0x3d353d35,0xbb49bd80,0xbd223d46,0x3d7dbc16,
0xbd35bd35,0xbc163d7d,0x3d62bcf1,0xbd67bcdb,0x3c483d7b,0x3d2cbd3e,0xbd7fbbc9,0x3d043d5c,0x3cc4bd6d,0xbd783c79,0x3d463d22,0x3b49bd80,0xbd553d0e,0x3d713cac,0xbc95bd75,0xbd183d4e,
0x3d80,0x3d4ebd18,0xbd75bc95,0x3cac3d71,0x3d0ebd55,0xbd803b49,0x3d223d46,0x3c79bd78,0xbd6d3cc4,0x3d5c3d04,0xbbc9bd7f,0xbd3e3d2c,0x3d7b3c48,0xbcdbbd67,0xbcf13d62,0x3d7dbc16,
0x3d0ebd55,0xbd7dbc16,0x3c953d75,0x3d3ebd2c,0x3d353d35,0x3cacbd71,0xbd7f3bc9,0x3d043d5c,0xbc483d7b,0x3d78bc79,0xbd22bd46,0xbcdb3d67,0xbd6dbcc4,0x3b493d80,0x3d62bcf1,0xbd4ebd18,
0x3d7bbc48,0xbd18bd4e,0xbcf13d62,0x3d803b49,0x3d80,0x3d67bcdb,0xbd46bd22,0xbc793d78,0xbd553d0e,0x3d5c3d04,0x3bc9bd7f,0xbd713cac,0xbcc4bd6d,0xbd2c3d3e,0x3d753c95,0xbc16bd7d,
0xbcc43d6d,0x3d7d3c16,0xbbc9bd7f,0xbd713cac,0x3d0e3d55,0x3d2cbd3e,0xbd62bcf1,0xbc793d78,0xbd35bd35,0xbd043d5c,0x3d753c95,0x3b49bd80,0xbd7b3c48,0x3cdb3d67,0x3d46bd22,0xbd4ebd18,
0x3d6dbcc4,0xbd18bd4e,0xbd223d46,0x3d673cdb,0x3c48bd7b,0xbd803b49,0x3c953d75,0x3d5cbd04,0x3d80,0x3d78bc79,0xbcf1bd62,0xbd3e3d2c,0x3d553d0e,0x3cacbd71,0xbd7fbbc9,0x3c163d7d,
0x3d7b3c48,0x3c16bd7d,0xbd7fbbc9,0xbb493d80,0x3d6d3cc4,0x3cacbd71,0xbd75bc95,0xbc793d78,0x3d553d0e,0x3d04bd5c,0xbd62bcf1,0xbcdb3d67,0x3d353d35,0x3d2cbd3e,0xbd46bd22,0xbd183d4e,
0x3d0e3d55,0x3d4ebd18,0xbd22bd46,0xbd3e3d2c,0x3cc43d6d,0x3d67bcdb,0xbcf1bd62,0xbd5c3d04,0x3c483d7b,0x3d78bc79,0xbc95bd75,0xbd713cac,0x3d80,0x3d80bb49,0xbbc9bd7f,0xbd7d3c16,
0xbd800000,0x3d7d3c16,0xbd75bc95,0x3d673cdb,0xbd55bd0e,0x3d3e3d2c,0xbd22bd46,0x3d043d5c,0xbcc4bd6d,0x3c793d78,0xbbc9bd7f,0xbb493d80,0x3c48bd7b,0xbcac3d71,0x3cf1bd62,0xbd183d4e,
0x3d35bd35,0xbd4e3d18,0x3d62bcf1,0xbd713cac,0x3d7bbc48,0xbd803b49,0x3d7f3bc9,0xbd78bc79,0x3d6d3cc4,0xbd5cbd04,0x3d463d22,0xbd2cbd3e,0x3d0e3d55,0xbcdbbd67,0x3c953d75,0xbc16bd7d,
0xbc48bd7b,0xbc163d7d,0x3cf1bd62,0xbd3e3d2c,0xbd800000,0x3d713cac,0xbd46bd22,0x3d043d5c,0x3d0e3d55,0xbc79bd78,0xbbc93d7f,0x3cdbbd67,0x3d6dbcc4,0xbd803b49,0x3d753c95,0xbd4ebd18,
0xbd55bd0e,0x3d183d4e,0xbc95bd75,0xbb493d80,0xbd353d35,0x3d67bcdb,0xbd7f3bc9,0x3d783c79,0x3d7b3c48,0xbd5cbd04,0x3d223d46,0xbcacbd71,0x3cc4bd6d,0xbd2c3d3e,0x3d62bcf1,0xbd7d3c16,
0x3cc43d6d,0x3c16bd7d,0xbd223d46,0x3d71bcac,0xbd7bbc48,0x3d3e3d2c,0xbc95bd75,0xbc793d78,0xbd800000,0x3d5c3d04,0xbcf1bd62,0xbb493d80,0x3d0ebd55,0xbd673cdb,0x3d7f3bc9,0xbd4ebd18,
0xbd6dbcc4,0x3d183d4e,0xbbc9bd7f,0xbcdb3d67,0x3d55bd0e,0xbd803b49,0x3d623cf1,0xbd04bd5c,0x3d35bd35,0xbd783c79,0x3d753c95,0xbd2cbd3e,0x3c483d7b,0x3cacbd71,0xbd463d22,0x3d7dbc16,
0x3d55bd0e,0xbd7dbc16,0x3d223d46,0x3b49bd80,0xbd6d3cc4,0x3d713cac,0xbcf1bd62,0xbc793d78,0x3d7bbc48,0xbd5cbd04,0x3c953d75,0x3cdbbd67,0xbd800000,0x3d3e3d2c,0xbbc9bd7f,0xbd183d4e,
0x3c48bd7b,0xbd4e3d18,0x3d7f3bc9,0xbd2cbd3e,0xbcc43d6d,0x3d67bcdb,0xbd75bc95,0x3d043d5c,0x3d0ebd55,0xbd783c79,0x3d623cf1,0xbcacbd71,0xbd353d35,0x3d80bb49,0xbd46bd22,0x3c163d7d,
0x3d35bd35,0xbd7dbc16,0x3cf13d62,0x3cdbbd67,0xbd7b3c48,0x3d3e3d2c,0x3bc9bd7f,0xbd5c3d04,0x3d6d3cc4,0xbc79bd78,0xbd223d46,0x3d803b49,0xbd0ebd55,0xbcac3d71,0x3d75bc95,0xbd4ebd18,
0xbd800000,0x3d183d4e,0x3c95bd75,0xbd713cac,0x3d553d0e,0xbb49bd80,0xbd463d22,0x3d783c79,0xbcc4bd6d,0xbd043d5c,0x3d7fbbc9,0xbd2cbd3e,0xbc483d7b,0x3d67bcdb,0xbd62bcf1,0x3c163d7d,
0x3d553d0e,0x3c16bd7d,0xbd753c95,0x3d2c3d3e,0xbd353d35,0x3d713cac,0xbbc9bd7f,0xbd5c3d04,0xbd7bbc48,0x3c793d78,0x3d46bd22,0xbd67bcdb,0x3cc4bd6d,0xbd803b49,0x3cf13d62,0x3d18bd4e,
0x3c483d7b,0x3d4ebd18,0xbd62bcf1,0xbb493d80,0xbd800000,0x3cdb3d67,0x3d22bd46,0xbd78bc79,0xbd0ebd55,0xbd043d5c,0x3d7f3bc9,0xbcacbd71,0x3d6dbcc4,0xbd3ebd2c,0xbc953d75,0x3d7dbc16,
0xbd6dbcc4,0xbc163d7d,0x3d7fbbc9,0xbcacbd71,0xbd553d0e,0x3d3e3d2c,0x3cf1bd62,0xbd78bc79,0x3d35bd35,0xbd5cbd04,0xbc953d75,0x3d803b49,0xbc48bd7b,0xbd673cdb,0x3d223d46,0x3d18bd4e,
0x3cc43d6d,0x3d4ebd18,0xbd46bd22,0xbcdb3d67,0x3d7b3c48,0xbb49bd80,0xbd753c95,0x3d043d5c,0xbd800000,0x3c793d78,0x3d62bcf1,0xbd2cbd3e,0xbd0e3d55,0x3d713cac,0x3bc9bd7f,0xbd7d3c16,
0xbc483d7b,0x3d7d3c16,0x3bc9bd7f,0xbd80bb49,0xbcc43d6d,0x3d713cac,0x3c95bd75,0xbd78bc79,0xbd0e3d55,0x3d5c3d04,0x3cf1bd62,0xbd67bcdb,0xbd353d35,0x3d3e3d2c,0x3d22bd46,0xbd4ebd18,
0xbd553d0e,0x3d183d4e,0x3d46bd22,0xbd2cbd3e,0xbd6d3cc4,0x3cdb3d67,0x3d62bcf1,0xbd04bd5c,0xbd7b3c48,0x3c793d78,0x3d75bc95,0xbcacbd71,0xbd800000,0x3b493d80,0x3d7fbbc9,0xbc16bd7d,
0x3d80,0x3d7d3c16,0x3c95bd75,0xbd67bcdb,0xbd0e3d55,0x3d3e3d2c,0x3d46bd22,0xbd04bd5c,0xbd6d3cc4,0x3c793d78,0x3d7fbbc9,0x3b49bd80,0xbd7bbc48,0xbcac3d71,0x3d623cf1,0x3d18bd4e,
0xbd35bd35,0xbd4e3d18,0x3cf13d62,0x3d71bcac,0xbc48bd7b,0xbd803b49,0xbbc93d7f,0x3d783c79,0x3cc4bd6d,0xbd5cbd04,0xbd223d46,0x3d2c3d3e,0x3d55bd0e,0xbcdbbd67,0xbd753c95,0x3c163d7d,
0xbd7b3c48,0xbc163d7d,0x3d623cf1,0x3d3ebd2c,0x3d80,0x3d713cac,0x3d22bd46,0xbd04bd5c,0x3d55bd0e,0xbc79bd78,0xbd7fbbc9,0xbcdb3d67,0xbcc4bd6d,0xbd803b49,0xbc953d75,0x3d4e3d18,
0xbd0e3d55,0x3d183d4e,0x3d75bc95,0x3b49bd80,0x3d353d35,0x3d67bcdb,0xbbc9bd7f,0xbd78bc79,0x3c48bd7b,0xbd5cbd04,0xbd463d22,0x3cac3d71,0xbd6dbcc4,0xbd2c3d3e,0x3cf13d62,0x3d7dbc16,
0x3d6dbcc4,0x3c16bd7d,0xbd46bd22,0xbd713cac,0xbc483d7b,0x3d3e3d2c,0x3d75bc95,0x3c79bd78,0x3d80,0x3d5c3d04,0x3d62bcf1,0x3b49bd80,0xbd55bd0e,0xbd673cdb,0xbbc93d7f,0x3d4e3d18,
0xbcc43d6d,0x3d183d4e,0x3d7fbbc9,0x3cdbbd67,0xbd0ebd55,0xbd803b49,0xbcf13d62,0x3d043d5c,0xbd35bd35,0xbd783c79,0xbc953d75,0x3d2c3d3e,0x3d7bbc48,0x3cacbd71,0xbd22bd46,0xbd7d3c16,
0xbd0ebd55,0xbd7dbc16,0xbd463d22,0xbb493d80,0x3cc43d6d,0x3d713cac,0x3d62bcf1,0x3c79bd78,0xbc48bd7b,0xbd5cbd04,0xbd753c95,0xbcdb3d67,0x3d80,0x3d3e3d2c,0x3d7fbbc9,0x3d18bd4e,
0xbd7bbc48,0xbd4e3d18,0xbbc93d7f,0x3d2c3d3e,0x3d6d3cc4,0x3d67bcdb,0x3c95bd75,0xbd04bd5c,0xbd55bd0e,0xbd783c79,0xbcf13d62,0x3cac3d71,0x3d353d35,0x3d80bb49,0x3d22bd46,0xbc16bd7d,
0xbd35bd35,0xbd7dbc16,0xbd623cf1,0xbcdb3d67,0x3c483d7b,0x3d3e3d2c,0x3d7f3bc9,0x3d5cbd04,0x3cc4bd6d,0xbc79bd78,0xbd46bd22,0xbd80bb49,0xbd553d0e,0xbcac3d71,0x3c953d75,0x3d4e3d18,
0x3d80,0x3d183d4e,0x3d753c95,0x3d71bcac,0x3d0ebd55,0xbb49bd80,0xbd22bd46,0xbd78bc79,0xbd6d3cc4,0xbd043d5c,0x3bc93d7f,0x3d2c3d3e,0x3d7b3c48,0x3d67bcdb,0x3cf1bd62,0xbc16bd7d,
0x3d0ebd55,0x3c16bd7d,0xbc95bd75,0xbd2cbd3e,0x3d353d35,0x3d713cac,0x3d7fbbc9,0x3d5cbd04,0xbc483d7b,0x3c793d78,0x3d223d46,0x3d673cdb,0xbd6dbcc4,0xbd803b49,0xbd623cf1,0xbd183d4e,
0x3d7bbc48,0x3d4ebd18,0x3cf1bd62,0x3b49bd80,0x3d80,0x3cdb3d67,0x3d463d22,0x3d783c79,0xbd553d0e,0xbd043d5c,0xbbc93d7f,0x3cac3d71,0xbcc4bd6d,0xbd3ebd2c,0xbd75bc95,0xbd7d3c16,
0xbcc43d6d,0xbc163d7d,0x3bc93d7f,0x3cac3d71,0x3d0e3d55,0x3d3e3d2c,0x3d623cf1,0x3d783c79,0xbd35bd35,0xbd5cbd04,0xbd75bc95,0xbd80bb49,0xbd7b3c48,0xbd673cdb,0xbd463d22,0xbd183d4e,
0x3d6dbcc4,0x3d4ebd18,0x3d22bd46,0x3cdbbd67,0x3c48bd7b,0xbb49bd80,0xbc95bd75,0xbd04bd5c,0x3d80,0x3c793d78,0x3cf13d62,0x3d2c3d3e,0x3d553d0e,0x3d713cac,0x3d7f3bc9,0x3d7dbc16,
0x3d7b3c48,0x3d7d3c16,0x3d7f3bc9,0x3d803b49,0x3d6d3cc4,0x3d713cac,0x3d753c95,0x3d783c79,0x3d553d0e,0x3d5c3d04,0x3d623cf1,0x3d673cdb,0x3d353d35,0x3d3e3d2c,0x3d463d22,0x3d4e3d18,
0x3d0e3d55,0x3d183d4e,0x3d223d46,0x3d2c3d3e,0x3cc43d6d,0x3cdb3d67,0x3cf13d62,0x3d043d5c,0x3c483d7b,0x3c793d78,0x3c953d75,0x3cac3d71,0x3d80,0x3b493d80,0x3bc93d7f,0x3c163d7d,
0xbd800000,0xbc163d7d,0x3d753c95,0x3cdbbd67,0xbd55bd0e,0xbd2c3d3e,0x3d223d46,0x3d5cbd04,0xbcc4bd6d,0xbd783c79,0x3bc93d7f,0x3d803b49,0x3c48bd7b,0xbd71bcac,0xbcf13d62,0x3d4e3d18,
0x3d35bd35,0xbd18bd4e,0xbd623cf1,0x3cac3d71,0x3d7bbc48,0xbb49bd80,0xbd7fbbc9,0xbc793d78,0x3d6d3cc4,0x3d04bd5c,0xbd46bd22,0xbd3e3d2c,0x3d0e3d55,0x3d67bcdb,0xbc95bd75,0xbd7d3c16,
0xbc48bd7b,0xbd7dbc16,0xbcf13d62,0x3d2c3d3e,0xbd800000,0xbcac3d71,0x3d463d22,0x3d5cbd04,0x3d0e3d55,0x3d78bc79,0x3bc9bd7f,0xbd67bcdb,0x3d6dbcc4,0xbb49bd80,0xbd75bc95,0xbd183d4e,
0xbd55bd0e,0xbd4e3d18,0x3c953d75,0x3d803b49,0xbd353d35,0x3cdb3d67,0x3d7fbbc9,0x3c79bd78,0x3d7b3c48,0x3d04bd5c,0xbd22bd46,0xbd713cac,0x3cc4bd6d,0xbd3ebd2c,0xbd623cf1,0x3c163d7d,
0x3cc43d6d,0x3d7d3c16,0x3d22bd46,0xbcacbd71,0xbd7bbc48,0xbd2c3d3e,0x3c953d75,0x3d783c79,0xbd800000,0xbd043d5c,0x3cf13d62,0x3d803b49,0x3d0ebd55,0xbcdbbd67,0xbd7fbbc9,0xbd183d4e,
0xbd6dbcc4,0xbd4e3d18,0x3bc93d7f,0x3d673cdb,0x3d55bd0e,0xbb49bd80,0xbd62bcf1,0xbd5c3d04,0x3d35bd35,0xbc79bd78,0xbd75bc95,0xbd3e3d2c,0x3c483d7b,0x3d713cac,0x3d46bd22,0xbc16bd7d,
0x3d55bd0e,0x3c16bd7d,0xbd22bd46,0xbd80bb49,0xbd6d3cc4,0xbcac3d71,0x3cf13d62,0x3d783c79,0x3d7bbc48,0x3d04bd5c,0xbc95bd75,0xbd67bcdb,0xbd800000,0xbd2c3d3e,0x3bc93d7f,0x3d4e3d18,
0x3c48bd7b,0xbd18bd4e,0xbd7fbbc9,0xbd3e3d2c,0xbcc43d6d,0x3cdb3d67,0x3d753c95,0x3d5cbd04,0x3d0ebd55,0xbc79bd78,0xbd62bcf1,0xbd713cac,0xbd353d35,0x3b493d80,0x3d463d22,0x3d7dbc16,
0x3d35bd35,0x3c16bd7d,0xbcf1bd62,0xbd67bcdb,0xbd7b3c48,0xbd2c3d3e,0xbbc93d7f,0x3d043d5c,0x3d6d3cc4,0x3d78bc79,0x3d22bd46,0x3b49bd80,0xbd0ebd55,0xbd71bcac,0xbd753c95,0xbd183d4e,
0xbd800000,0xbd4e3d18,0xbc953d75,0x3cac3d71,0x3d553d0e,0x3d80bb49,0x3d46bd22,0x3c79bd78,0xbcc4bd6d,0xbd5cbd04,0xbd7f3bc9,0xbd3e3d2c,0xbc483d7b,0x3cdb3d67,0x3d623cf1,0x3d7dbc16,
0x3d553d0e,0x3d7d3c16,0x3d75bc95,0x3d3ebd2c,0xbd353d35,0xbcac3d71,0x3bc93d7f,0x3d043d5c,0xbd7bbc48,0xbd783c79,0xbd463d22,0xbcdb3d67,0x3cc4bd6d,0xbb49bd80,0xbcf1bd62,0xbd4ebd18,
0x3c483d7b,0x3d183d4e,0x3d623cf1,0x3d803b49,0xbd800000,0xbd673cdb,0xbd223d46,0xbc793d78,0xbd0ebd55,0xbd5cbd04,0xbd7fbbc9,0xbd713cac,0x3d6dbcc4,0x3d2cbd3e,0x3c95bd75,0xbc16bd7d,
0xbd6dbcc4,0xbd7dbc16,0xbd7f3bc9,0xbd713cac,0xbd553d0e,0xbd2c3d3e,0xbcf13d62,0xbc793d78,0x3d35bd35,0x3d04bd5c,0x3c95bd75,0x3b49bd80,0xbc48bd7b,0xbcdbbd67,0xbd22bd46,0xbd4ebd18,
0x3cc43d6d,0x3d183d4e,0x3d463d22,0x3d673cdb,0x3d7b3c48,0x3d80bb49,0x3d75bc95,0x3d5cbd04,0xbd800000,0xbd783c79,0xbd623cf1,0xbd3e3d2c,0xbd0e3d55,0xbcac3d71,0xbbc93d7f,0x3c163d7d,
0xbc483d7b,0xbc163d7d,0xbbc93d7f,0xbb493d80,0xbcc43d6d,0xbcac3d71,0xbc953d75,0xbc793d78,0xbd0e3d55,0xbd043d5c,0xbcf13d62,0xbcdb3d67,0xbd353d35,0xbd2c3d3e,0xbd223d46,0xbd183d4e,
0xbd553d0e,0xbd4e3d18,0xbd463d22,0xbd3e3d2c,0xbd6d3cc4,0xbd673cdb,0xbd623cf1,0xbd5c3d04,0xbd7b3c48,0xbd783c79,0xbd753c95,0xbd713cac,0xbd800000,0xbd803b49,0xbd7f3bc9,0xbd7d3c16,
0x3f003f00,0xbf003f00,0x3f003f00,0xbf003f00,0x3f003f00,0xbf003f00,0x3f003f00,0xbf003f00,0x3f003f00,0xbf003f00,0x3f003f00,0xbf003f00,0x3f003f00,0xbf003f00,0x3f003f00,0xbf003f00,
0x3eff3f00,0xbd490000,0x3ea23eb5,0xbec6beb5,0x3ef53efb,0xbe15bdc8,0x3e713e8e,0xbee2bed5,0x3ee23eed,0xbe71be44,0x3e153e44,0xbef5beed,0x3ec63ed5,0xbea2be8e,0x3d493dc8,0xbeffbefb,
0x3efb3f00,0xbdc80000,0xbdc80000,0xbefbbf00,0x3ed53eed,0xbe8ebe44,0xbe8ebe44,0xbed5beed,0x3e8e3eb5,0xbed5beb5,0xbed5beb5,0xbe8ebeb5,0x3dc83e44,0xbefbbeed,0xbefbbeed,0xbdc8be44,
0x3ef53f00,0xbe150000,0xbee2beb5,0xbe71beb5,0x3ea23ed5,0xbec6be8e,0xbeffbefb,0x3d49bdc8,0x3d493e44,0xbeffbeed,0xbec6beed,0x3ea23e44,0xbe71bdc8,0xbee2befb,0xbe15be8e,0x3ef53ed5,
0x3eed3f00,0xbe440000,0xbeedbf00,0x3e440000,0x3e443eb5,0xbeedbeb5,0xbe44beb5,0x3eed3eb5,0xbe440000,0xbeedbf00,0x3e440000,0x3eed3f00,0xbeedbeb5,0xbe44beb5,0x3eed3eb5,0x3e443eb5,
0x3ee23f00,0xbe710000,0xbe15beb5,0x3ef53eb5,0x3d493e8e,0xbeffbed5,0x3ea23dc8,0x3ec63efb,0xbec6be44,0xbea2beed,0x3eff3eed,0xbd493e44,0xbef5befb,0x3e15bdc8,0x3e713ed5,0xbee2be8e,
0x3ed53f00,0xbe8e0000,0x3e8e0000,0x3ed53f00,0xbdc83e44,0xbefbbeed,0x3efb3eed,0xbdc83e44,0xbefbbeb5,0xbdc8beb5,0x3dc83eb5,0xbefbbeb5,0xbe8ebeed,0x3ed53e44,0xbed5be44,0xbe8ebeed,
0x3ec63f00,0xbea20000,0x3eff3eb5,0x3d493eb5,0xbe713dc8,0xbee2befb,0x3e153ed5,0xbef5be8e,0xbef5beed,0x3e15be44,0xbee2be44,0xbe71beed,0x3d49be8e,0x3eff3ed5,0xbea2befb,0x3ec63dc8,
0x3f00,0xbf000000,0x3f00,0xbf000000,0xbf00,0x3f000000,0xbf00,0x3f000000,0x3f00,0xbf000000,0x3f00,0xbf000000,0xbf00,0x3f000000,0xbf00,0x3f000000,
0xbd493f00,0xbeff0000,0xbec63eb5,0xbea2beb5,0x3e15befb,0x3ef53dc8,0x3ee2be8e,0x3e713ed5,0xbe713eed,0xbee2be44,0xbef53e44,0xbe15beed,0x3ea2bed5,0x3ec63e8e,0x3effbdc8,0x3d493efb,
0xbdc83f00,0xbefb0000,0xbefb0000,0x3dc8bf00,0x3e8ebeed,0x3ed53e44,0x3ed53e44,0xbe8e3eed,0xbed53eb5,0xbe8ebeb5,0xbe8ebeb5,0x3ed5beb5,0x3efbbe44,0x3dc83eed,0x3dc83eed,0xbefb3e44,
0xbe153f00,0xbef50000,0xbe71beb5,0x3ee2beb5,0x3ec6bed5,0x3ea23e8e,0xbd493efb,0xbeff3dc8,0xbeff3e44,0xbd49beed,0x3ea2beed,0x3ec63e44,0x3ee23dc8,0xbe713efb,0xbef53e8e,0xbe15bed5,
0xbe443f00,0xbeed0000,0x3e44bf00,0x3eed0000,0x3eedbeb5,0x3e443eb5,0xbeed3eb5,0xbe44beb5,0xbeed0000,0x3e44bf00,0x3eed0000,0xbe443f00,0x3e443eb5,0xbeed3eb5,0xbe44beb5,0x3eedbeb5,
0xbe713f00,0xbee20000,0x3ef5beb5,0x3e153eb5,0x3effbe8e,0x3d493ed5,0xbec6bdc8,0x3ea2befb,0xbea2be44,0x3ec6beed,0xbd493eed,0xbeff3e44,0xbe153efb,0xbef53dc8,0x3ee2bed5,0x3e713e8e,
0xbe8e3f00,0xbed50000,0x3ed50000,0xbe8e3f00,0x3efbbe44,0xbdc83eed,0x3dc8beed,0x3efbbe44,0xbdc8beb5,0x3efbbeb5,0xbefb3eb5,0xbdc8beb5,0xbed53eed,0xbe8ebe44,0x3e8e3e44,0xbed53eed,
0xbea23f00,0xbec60000,0x3d493eb5,0xbeff3eb5,0x3ee2bdc8,0xbe713efb,0x3ef5bed5,0x3e153e8e,0x3e15beed,0x3ef5be44,0xbe71be44,0x3ee2beed,0xbeff3e8e,0x3d49bed5,0xbec63efb,0xbea2bdc8,
0x3eb53f00,0xbeb50000,0x3eb53f00,0xbeb50000,0xbeb50000,0xbeb5bf00,0xbeb50000,0xbeb5bf00,0xbeb5bf00,0x3eb50000,0xbeb5bf00,0x3eb50000,0x3eb50000,0x3eb53f00,0x3eb50000,0x3eb53f00,
0xbeff3f00,0x3d490000,0xbea23eb5,0x3ec6beb5,0xbef53efb,0x3e15bdc8,0xbe713e8e,0x3ee2bed5,0xbee23eed,0x3e71be44,0xbe153e44,0x3ef5beed,0xbec63ed5,0x3ea2be8e,0xbd493dc8,0x3effbefb,
0xbefb3f00,0x3dc80000,0x3dc80000,0x3efbbf00,0xbed53eed,0x3e8ebe44,0x3e8ebe44,0x3ed5beed,0xbe8e3eb5,0x3ed5beb5,0x3ed5beb5,0x3e8ebeb5,0xbdc83e44,0x3efbbeed,0x3efbbeed,0x3dc8be44,
0xbef53f00,0x3e150000,0x3ee2beb5,0x3e71beb5,0xbea23ed5,0x3ec6be8e,0x3effbefb,0xbd49bdc8,0xbd493e44,0x3effbeed,0x3ec6beed,0xbea23e44,0x3e71bdc8,0x3ee2befb,0x3e15be8e,0xbef53ed5,
0xbeed3f00,0x3e440000,0x3eedbf00,0xbe440000,0xbe443eb5,0x3eedbeb5,0x3e44beb5,0xbeed3eb5,0x3e440000,0x3eedbf00,0xbe440000,0xbeed3f00,0x3eedbeb5,0x3e44beb5,0xbeed3eb5,0xbe443eb5,
0xbee23f00,0x3e710000,0x3e15beb5,0xbef53eb5,0xbd493e8e,0x3effbed5,0xbea23dc8,0xbec63efb,0x3ec6be44,0x3ea2beed,0xbeff3eed,0x3d493e44,0x3ef5befb,0xbe15bdc8,0xbe713ed5,0x3ee2be8e,
0xbed53f00,0x3e8e0000,0xbe8e0000,0xbed53f00,0x3dc83e44,0x3efbbeed,0xbefb3eed,0x3dc83e44,0x3efbbeb5,0x3dc8beb5,0xbdc83eb5,0x3efbbeb5,0x3e8ebeed,0xbed53e44,0x3ed5be44,0x3e8ebeed,
0xbec63f00,0x3ea20000,0xbeff3eb5,0xbd493eb5,0x3e713dc8,0x3ee2befb,0xbe153ed5,0x3ef5be8e,0x3ef5beed,0xbe15be44,0x3ee2be44,0x3e71beed,0xbd49be8e,0xbeff3ed5,0x3ea2befb,0xbec63dc8,
0xbeb53f00,0xbeb50000,0xbeb53f00,0xbeb50000,0x3eb50000,0xbeb53f00,0x3eb50000,0xbeb53f00,0x3eb5bf00,0x3eb50000,0x3eb5bf00,0x3eb50000,0xbeb50000,0x3eb5bf00,0xbeb50000,0x3eb5bf00,
0x3d493f00,0x3eff0000,0x3ec63eb5,0x3ea2beb5,0xbe15befb,0xbef53dc8,0xbee2be8e,0xbe713ed5,0x3e713eed,0x3ee2be44,0x3ef53e44,0x3e15beed,0xbea2bed5,0xbec63e8e,0xbeffbdc8,0xbd493efb,
0x3dc83f00,0x3efb0000,0x3efb0000,0xbdc8bf00,0xbe8ebeed,0xbed53e44,0xbed53e44,0x3e8e3eed,0x3ed53eb5,0x3e8ebeb5,0x3e8ebeb5,0xbed5beb5,0xbefbbe44,0xbdc83eed,0xbdc83eed,0x3efb3e44,
0x3e153f00,0x3ef50000,0x3e71beb5,0xbee2beb5,0xbec6bed5,0xbea23e8e,0x3d493efb,0x3eff3dc8,0x3eff3e44,0x3d49beed,0xbea2beed,0xbec63e44,0xbee23dc8,0x3e713efb,0x3ef53e8e,0x3e15bed5,
0x3e443f00,0x3eed0000,0xbe44bf00,0xbeed0000,0xbeedbeb5,0xbe443eb5,0x3eed3eb5,0x3e44beb5,0x3eed0000,0xbe44bf00,0xbeed0000,0x3e443f00,0xbe443eb5,0x3eed3eb5,0x3e44beb5,0xbeedbeb5,
0x3e713f00,0x3ee20000,0xbef5beb5,0xbe153eb5,0xbeffbe8e,0xbd493ed5,0x3ec6bdc8,0xbea2befb,0x3ea2be44,0xbec6beed,0x3d493eed,0x3eff3e44,0x3e153efb,0x3ef53dc8,0xbee2bed5,0xbe713e8e,
0x3e8e3f00,0x3ed50000,0xbed50000,0x3e8e3f00,0xbefbbe44,0x3dc83eed,0xbdc8beed,0xbefbbe44,0x3dc8beb5,0xbefbbeb5,0x3efb3eb5,0x3dc8beb5,0x3ed53eed,0x3e8ebe44,0xbe8e3e44,0x3ed53eed,
0x3ea23f00,0x3ec60000,0xbd493eb5,0x3eff3eb5,0xbee2bdc8,0x3e713efb,0xbef5bed5,0xbe153e8e,0xbe15beed,0xbef5be44,0x3e71be44,0xbee2beed,0x3eff3e8e,0xbd49bed5,0x3ec63efb,0x3ea2bdc8,
0x3f003f00,0xbf003f00,0x3f003f00,0xbf003f00,0x3f003f00,0xbf003f00,0x3f003f00,0xbf003f00,0x3f003f00,0xbf003f00,0x3f003f00,0xbf003f00,0x3f003f00,0xbf003f00,0x3f003f00,0xbf003f00,
0xbd490000,0xbeffbf00,0xbec6beb5,0xbea2beb5,0xbe15bdc8,0xbef5befb,0xbee2bed5,0xbe71be8e,0xbe71be44,0xbee2beed,0xbef5beed,0xbe15be44,0xbea2be8e,0xbec6bed5,0xbeffbefb,0xbd49bdc8,
0xbefbbf00,0x3dc80000,0x3dc80000,0x3efb3f00,0xbed5beed,0x3e8e3e44,0x3e8e3e44,0x3ed53eed,0xbe8ebeb5,0x3ed53eb5,0x3ed53eb5,0x3e8e3eb5,0xbdc8be44,0x3efb3eed,0x3efb3eed,0x3dc83e44,
0x3e150000,0x3ef53f00,0x3e713eb5,0xbee2beb5,0x3ec63e8e,0x3ea23ed5,0xbd493dc8,0xbeffbefb,0x3eff3eed,0x3d493e44,0xbea2be44,0xbec6beed,0x3ee23efb,0xbe71bdc8,0xbef5bed5,0xbe15be8e,
0x3eed3f00,0xbe440000,0xbeedbf00,0x3e440000,0x3e443eb5,0xbeedbeb5,0xbe44beb5,0x3eed3eb5,0xbe440000,0xbeedbf00,0x3e440000,0x3eed3f00,0xbeedbeb5,0xbe44beb5,0x3eed3eb5,0x3e443eb5,
0xbe710000,0xbee2bf00,0x3ef53eb5,0x3e153eb5,0xbeffbed5,0xbd49be8e,0x3ec63efb,0xbea2bdc8,0xbea2beed,0x3ec63e44,0xbd493e44,0xbeffbeed,0x3e15bdc8,0x3ef53efb,0xbee2be8e,0xbe71bed5,
0xbed5bf00,0x3e8e0000,0xbe8e0000,0xbed5bf00,0x3dc8be44,0x3efb3eed,0xbefbbeed,0x3dc8be44,0x3efb3eb5,0x3dc83eb5,0xbdc8beb5,0x3efb3eb5,0x3e8e3eed,0xbed5be44,0x3ed53e44,0x3e8e3eed,
0x3ea20000,0x3ec63f00,0xbd49beb5,0x3eff3eb5,0x3ee23efb,0xbe713dc8,0x3ef53e8e,0x3e153ed5,0xbe153e44,0xbef5beed,0x3e713eed,0xbee2be44,0xbeffbed5,0x3d49be8e,0xbec6bdc8,0xbea2befb,
0x3f00,0xbf000000,0x3f00,0xbf000000,0xbf00,0x3f000000,0xbf00,0x3f000000,0x3f00,0xbf000000,0x3f00,0xbf000000,0xbf00,0x3f000000,0xbf00,0x3f000000,
0xbeff0000,0x3d49bf00,0xbea2beb5,0x3ec6beb5,0x3ef53dc8,0xbe153efb,0x3e713ed5,0xbee23e8e,0xbee2be44,0x3e71beed,0xbe15beed,0x3ef5be44,0x3ec63e8e,0xbea23ed5,0x3d493efb,0xbeff3dc8,
0x3dc8bf00,0x3efb0000,0x3efb0000,0xbdc83f00,0xbe8e3eed,0xbed5be44,0xbed5be44,0x3e8ebeed,0x3ed5beb5,0x3e8e3eb5,0x3e8e3eb5,0xbed53eb5,0xbefb3e44,0xbdc8beed,0xbdc8beed,0x3efbbe44,
0x3ef50000,0xbe153f00,0xbee23eb5,0xbe71beb5,0xbea2be8e,0x3ec6bed5,0x3effbdc8,0xbd493efb,0x3d493eed,0xbeff3e44,0xbec6be44,0x3ea2beed,0x3e71befb,0x3ee23dc8,0x3e153ed5,0xbef53e8e,
0xbe443f00,0xbeed0000,0x3e44bf00,0x3eed0000,0x3eedbeb5,0x3e443eb5,0xbeed3eb5,0xbe44beb5,0xbeed0000,0x3e44bf00,0x3eed0000,0xbe443f00,0x3e443eb5,0xbeed3eb5,0xbe44beb5,0x3eedbeb5,
0xbee20000,0x3e71bf00,0x3e153eb5,0xbef53eb5,0x3d493ed5,0xbeff3e8e,0x3ea2befb,0x3ec63dc8,0x3ec6beed,0x3ea23e44,0xbeff3e44,0x3d49beed,0xbef53dc8,0x3e15befb,0x3e713e8e,0xbee23ed5,
0x3e8ebf00,0x3ed50000,0xbed50000,0x3e8ebf00,0xbefb3e44,0x3dc8beed,0xbdc83eed,0xbefb3e44,0x3dc83eb5,0xbefb3eb5,0x3efbbeb5,0x3dc83eb5,0x3ed5beed,0x3e8e3e44,0xbe8ebe44,0x3ed5beed,
0x3ec60000,0xbea23f00,0x3effbeb5,0x3d493eb5,0x3e71befb,0x3ee2bdc8,0xbe15be8e,0x3ef5bed5,0xbef53e44,0x3e15beed,0xbee23eed,0xbe71be44,0xbd493ed5,0xbeff3e8e,0x3ea23dc8,0xbec63efb,
0x3eb53f00,0xbeb50000,0x3eb53f00,0xbeb50000,0xbeb50000,0xbeb5bf00,0xbeb50000,0xbeb5bf00,0xbeb5bf00,0x3eb50000,0xbeb5bf00,0x3eb50000,0x3eb50000,0x3eb53f00,0x3eb50000,0x3eb53f00,
0x3d490000,0x3effbf00,0x3ec6beb5,0x3ea2beb5,0x3e15bdc8,0x3ef5befb,0x3ee2bed5,0x3e71be8e,0x3e71be44,0x3ee2beed,0x3ef5beed,0x3e15be44,0x3ea2be8e,0x3ec6bed5,0x3effbefb,0x3d49bdc8,
0x3efbbf00,0xbdc80000,0xbdc80000,0xbefb3f00,0x3ed5beed,0xbe8e3e44,0xbe8e3e44,0xbed53eed,0x3e8ebeb5,0xbed53eb5,0xbed53eb5,0xbe8e3eb5,0x3dc8be44,0xbefb3eed,0xbefb3eed,0xbdc83e44,
0xbe150000,0xbef53f00,0xbe713eb5,0x3ee2beb5,0xbec63e8e,0xbea23ed5,0x3d493dc8,0x3effbefb,0xbeff3eed,0xbd493e44,0x3ea2be44,0x3ec6beed,0xbee23efb,0x3e71bdc8,0x3ef5bed5,0x3e15be8e,
0xbeed3f00,0x3e440000,0x3eedbf00,0xbe440000,0xbe443eb5,0x3eedbeb5,0x3e44beb5,0xbeed3eb5,0x3e440000,0x3eedbf00,0xbe440000,0xbeed3f00,0x3eedbeb5,0x3e44beb5,0xbeed3eb5,0xbe443eb5,
0x3e710000,0x3ee2bf00,0xbef53eb5,0xbe153eb5,0x3effbed5,0x3d49be8e,0xbec63efb,0x3ea2bdc8,0x3ea2beed,0xbec63e44,0x3d493e44,0x3effbeed,0xbe15bdc8,0xbef53efb,0x3ee2be8e,0x3e71bed5,
0x3ed5bf00,0xbe8e0000,0x3e8e0000,0x3ed5bf00,0xbdc8be44,0xbefb3eed,0x3efbbeed,0xbdc8be44,0xbefb3eb5,0xbdc83eb5,0x3dc8beb5,0xbefb3eb5,0xbe8e3eed,0x3ed5be44,0xbed53e44,0xbe8e3eed,
0xbea20000,0xbec63f00,0x3d49beb5,0xbeff3eb5,0xbee23efb,0x3e713dc8,0xbef53e8e,0xbe153ed5,0x3e153e44,0x3ef5beed,0xbe713eed,0x3ee2be44,0x3effbed5,0xbd49be8e,0x3ec6bdc8,0x3ea2befb,
0xbeb53f00,0xbeb50000,0xbeb53f00,0xbeb50000,0x3eb50000,0xbeb53f00,0x3eb50000,0xbeb53f00,0x3eb5bf00,0x3eb50000,0x3eb5bf00,0x3eb50000,0xbeb50000,0x3eb5bf00,0xbeb50000,0x3eb5bf00,
0x3eff0000,0xbd49bf00,0x3ea2beb5,0xbec6beb5,0xbef53dc8,0x3e153efb,0xbe713ed5,0x3ee23e8e,0x3ee2be44,0xbe71beed,0x3e15beed,0xbef5be44,0xbec63e8e,0x3ea23ed5,0xbd493efb,0x3eff3dc8,
0xbdc8bf00,0xbefb0000,0xbefb0000,0x3dc83f00,0x3e8e3eed,0x3ed5be44,0x3ed5be44,0xbe8ebeed,0xbed5beb5,0xbe8e3eb5,0xbe8e3eb5,0x3ed53eb5,0x3efb3e44,0x3dc8beed,0x3dc8beed,0xbefbbe44,
0xbef50000,0x3e153f00,0x3ee23eb5,0x3e71beb5,0x3ea2be8e,0xbec6bed5,0xbeffbdc8,0x3d493efb,0xbd493eed,0x3eff3e44,0x3ec6be44,0xbea2beed,0xbe71befb,0xbee23dc8,0xbe153ed5,0x3ef53e8e,
0x3e443f00,0x3eed0000,0xbe44bf00,0xbeed0000,0xbeedbeb5,0xbe443eb5,0x3eed3eb5,0x3e44beb5,0x3eed0000,0xbe44bf00,0xbeed0000,0x3e443f00,0xbe443eb5,0x3eed3eb5,0x3e44beb5,0xbeedbeb5,
0x3ee20000,0xbe71bf00,0xbe153eb5,0x3ef53eb5,0xbd493ed5,0x3eff3e8e,0xbea2befb,0xbec63dc8,0xbec6beed,0xbea23e44,0x3eff3e44,0xbd49beed,0x3ef53dc8,0xbe15befb,0xbe713e8e,0x3ee23ed5,
0xbe8ebf00,0xbed50000,0x3ed50000,0xbe8ebf00,0x3efb3e44,0xbdc8beed,0x3dc83eed,0x3efb3e44,0xbdc83eb5,0x3efb3eb5,0xbefbbeb5,0xbdc83eb5,0xbed5beed,0xbe8e3e44,0x3e8ebe44,0xbed5beed,
0xbec60000,0x3ea23f00,0xbeffbeb5,0xbd493eb5,0xbe71befb,0xbee2bdc8,0x3e15be8e,0xbef5bed5,0x3ef53e44,0xbe15beed,0x3ee23eed,0x3e71be44,0x3d493ed5,0x3eff3e8e,0xbea23dc8,0x3ec63efb,
0x3f003f00,0xbf003f00,0x3f003f00,0xbf003f00,0x3f003f00,0xbf003f00,0x3f003f00,0xbf003f00,0x3f003f00,0xbf003f00,0x3f003f00,0xbf003f00,0x3f003f00,0xbf003f00,0x3f003f00,0xbf003f00,
0xbeffbf00,0x3d490000,0xbea2beb5,0x3ec63eb5,0xbef5befb,0x3e153dc8,0xbe71be8e,0x3ee23ed5,0xbee2beed,0x3e713e44,0xbe15be44,0x3ef53eed,0xbec6bed5,0x3ea23e8e,0xbd49bdc8,0x3eff3efb,
0x3efb3f00,0xbdc80000,0xbdc80000,0xbefbbf00,0x3ed53eed,0xbe8ebe44,0xbe8ebe44,0xbed5beed,0x3e8e3eb5,0xbed5beb5,0xbed5beb5,0xbe8ebeb5,0x3dc83e44,0xbefbbeed,0xbefbbeed,0xbdc8be44,
0xbef5bf00,0x3e150000,0x3ee23eb5,0x3e713eb5,0xbea2bed5,0x3ec63e8e,0x3eff3efb,0xbd493dc8,0xbd49be44,0x3eff3eed,0x3ec63eed,0xbea2be44,0x3e713dc8,0x3ee23efb,0x3e153e8e,0xbef5bed5,
0x3eed3f00,0xbe440000,0xbeedbf00,0x3e440000,0x3e443eb5,0xbeedbeb5,0xbe44beb5,0x3eed3eb5,0xbe440000,0xbeedbf00,0x3e440000,0x3eed3f00,0xbeedbeb5,0xbe44beb5,0x3eed3eb5,0x3e443eb5,
0xbee2bf00,0x3e710000,0x3e153eb5,0xbef5beb5,0xbd49be8e,0x3eff3ed5,0xbea2bdc8,0xbec6befb,0x3ec63e44,0x3ea23eed,0xbeffbeed,0x3d49be44,0x3ef53efb,0xbe153dc8,0xbe71bed5,0x3ee23e8e,
0x3ed53f00,0xbe8e0000,0x3e8e0000,0x3ed53f00,0xbdc83e44,0xbefbbeed,0x3efb3eed,0xbdc83e44,0xbefbbeb5,0xbdc8beb5,0x3dc83eb5,0xbefbbeb5,0xbe8ebeed,0x3ed53e44,0xbed5be44,0xbe8ebeed,
0xbec6bf00,0x3ea20000,0xbeffbeb5,0xbd49beb5,0x3e71bdc8,0x3ee23efb,0xbe15bed5,0x3ef53e8e,0x3ef53eed,0xbe153e44,0x3ee23e44,0x3e713eed,0xbd493e8e,0xbeffbed5,0x3ea23efb,0xbec6bdc8,
0x3f00,0xbf000000,0x3f00,0xbf000000,0xbf00,0x3f000000,0xbf00,0x3f000000,0x3f00,0xbf000000,0x3f00,0xbf000000,0xbf00,0x3f000000,0xbf00,0x3f000000,
0x3d49bf00,0x3eff0000,0x3ec6beb5,0x3ea23eb5,0xbe153efb,0xbef5bdc8,0xbee23e8e,0xbe71bed5,0x3e71beed,0x3ee23e44,0x3ef5be44,0x3e153eed,0xbea23ed5,0xbec6be8e,0xbeff3dc8,0xbd49befb,
0xbdc83f00,0xbefb0000,0xbefb0000,0x3dc8bf00,0x3e8ebeed,0x3ed53e44,0x3ed53e44,0xbe8e3eed,0xbed53eb5,0xbe8ebeb5,0xbe8ebeb5,0x3ed5beb5,0x3efbbe44,0x3dc83eed,0x3dc83eed,0xbefb3e44,
0x3e15bf00,0x3ef50000,0x3e713eb5,0xbee23eb5,0xbec63ed5,0xbea2be8e,0x3d49befb,0x3effbdc8,0x3effbe44,0x3d493eed,0xbea23eed,0xbec6be44,0xbee2bdc8,0x3e71befb,0x3ef5be8e,0x3e153ed5,
0xbe443f00,0xbeed0000,0x3e44bf00,0x3eed0000,0x3eedbeb5,0x3e443eb5,0xbeed3eb5,0xbe44beb5,0xbeed0000,0x3e44bf00,0x3eed0000,0xbe443f00,0x3e443eb5,0xbeed3eb5,0xbe44beb5,0x3eedbeb5,
0x3e71bf00,0x3ee20000,0xbef53eb5,0xbe15beb5,0xbeff3e8e,0xbd49bed5,0x3ec63dc8,0xbea23efb,0x3ea23e44,0xbec63eed,0x3d49beed,0x3effbe44,0x3e15befb,0x3ef5bdc8,0xbee23ed5,0xbe71be8e,
0xbe8e3f00,0xbed50000,0x3ed50000,0xbe8e3f00,0x3efbbe44,0xbdc83eed,0x3dc8beed,0x3efbbe44,0xbdc8beb5,0x3efbbeb5,0xbefb3eb5,0xbdc8beb5,0xbed53eed,0xbe8ebe44,0x3e8e3e44,0xbed53eed,
0x3ea2bf00,0x3ec60000,0xbd49beb5,0x3effbeb5,0xbee23dc8,0x3e71befb,0xbef53ed5,0xbe15be8e,0xbe153eed,0xbef53e44,0x3e713e44,0xbee23eed,0x3effbe8e,0xbd493ed5,0x3ec6befb,0x3ea23dc8,
0x3eb53f00,0xbeb50000,0x3eb53f00,0xbeb50000,0xbeb50000,0xbeb5bf00,0xbeb50000,0xbeb5bf00,0xbeb5bf00,0x3eb50000,0xbeb5bf00,0x3eb50000,0x3eb50000,0x3eb53f00,0x3eb50000,0x3eb53f00,
0x3effbf00,0xbd490000,0x3ea2beb5,0xbec63eb5,0x3ef5befb,0xbe153dc8,0x3e71be8e,0xbee23ed5,0x3ee2beed,0xbe713e44,0x3e15be44,0xbef53eed,0x3ec6bed5,0xbea23e8e,0x3d49bdc8,0xbeff3efb,
0xbefb3f00,0x3dc80000,0x3dc80000,0x3efbbf00,0xbed53eed,0x3e8ebe44,0x3e8ebe44,0x3ed5beed,0xbe8e3eb5,0x3ed5beb5,0x3ed5beb5,0x3e8ebeb5,0xbdc83e44,0x3efbbeed,0x3efbbeed,0x3dc8be44,
0x3ef5bf00,0xbe150000,0xbee23eb5,0xbe713eb5,0x3ea2bed5,0xbec63e8e,0xbeff3efb,0x3d493dc8,0x3d49be44,0xbeff3eed,0xbec63eed,0x3ea2be44,0xbe713dc8,0xbee23efb,0xbe153e8e,0x3ef5bed5,
0xbeed3f00,0x3e440000,0x3eedbf00,0xbe440000,0xbe443eb5,0x3eedbeb5,0x3e44beb5,0xbeed3eb5,0x3e440000,0x3eedbf00,0xbe440000,0xbeed3f00,0x3eedbeb5,0x3e44beb5,0xbeed3eb5,0xbe443eb5,
0x3ee2bf00,0xbe710000,0xbe153eb5,0x3ef5beb5,0x3d49be8e,0xbeff3ed5,0x3ea2bdc8,0x3ec6befb,0xbec63e44,0xbea23eed,0x3effbeed,0xbd49be44,0xbef53efb,0x3e153dc8,0x3e71bed5,0xbee23e8e,
0xbed53f00,0x3e8e0000,0xbe8e0000,0xbed53f00,0x3dc83e44,0x3efbbeed,0xbefb3eed,0x3dc83e44,0x3efbbeb5,0x3dc8beb5,0xbdc83eb5,0x3efbbeb5,0x3e8ebeed,0xbed53e44,0x3ed5be44,0x3e8ebeed,
0x3ec6bf00,0xbea20000,0x3effbeb5,0x3d49beb5,0xbe71bdc8,0xbee23efb,0x3e15bed5,0xbef53e8e,0xbef53eed,0x3e153e44,0xbee23e44,0xbe713eed,0x3d493e8e,0x3effbed5,0xbea23efb,0x3ec6bdc8,
0xbeb53f00,0xbeb50000,0xbeb53f00,0xbeb50000,0x3eb50000,0xbeb53f00,0x3eb50000,0xbeb53f00,0x3eb5bf00,0x3eb50000,0x3eb5bf00,0x3eb50000,0xbeb50000,0x3eb5bf00,0xbeb50000,0x3eb5bf00,
0xbd49bf00,0xbeff0000,0xbec6beb5,0xbea23eb5,0x3e153efb,0x3ef5bdc8,0x3ee23e8e,0x3e71bed5,0xbe71beed,0xbee23e44,0xbef5be44,0xbe153eed,0x3ea23ed5,0x3ec6be8e,0x3eff3dc8,0x3d49befb,
0x3dc83f00,0x3efb0000,0x3efb0000,0xbdc8bf00,0xbe8ebeed,0xbed53e44,0xbed53e44,0x3e8e3eed,0x3ed53eb5,0x3e8ebeb5,0x3e8ebeb5,0xbed5beb5,0xbefbbe44,0xbdc83eed,0xbdc83eed,0x3efb3e44,
0xbe15bf00,0xbef50000,0xbe713eb5,0x3ee23eb5,0x3ec63ed5,0x3ea2be8e,0xbd49befb,0xbeffbdc8,0xbeffbe44,0xbd493eed,0x3ea23eed,0x3ec6be44,0x3ee2bdc8,0xbe71befb,0xbef5be8e,0xbe153ed5,
0x3e443f00,0x3eed0000,0xbe44bf00,0xbeed0000,0xbeedbeb5,0xbe443eb5,0x3eed3eb5,0x3e44beb5,0x3eed0000,0xbe44bf00,0xbeed0000,0x3e443f00,0xbe443eb5,0x3eed3eb5,0x3e44beb5,0xbeedbeb5,
0xbe71bf00,0xbee20000,0x3ef53eb5,0x3e15beb5,0x3eff3e8e,0x3d49bed5,0xbec63dc8,0x3ea23efb,0xbea23e44,0x3ec63eed,0xbd49beed,0xbeffbe44,0xbe15befb,0xbef5bdc8,0x3ee23ed5,0x3e71be8e,
0x3e8e3f00,0x3ed50000,0xbed50000,0x3e8e3f00,0xbefbbe44,0x3dc83eed,0xbdc8beed,0xbefbbe44,0x3dc8beb5,0xbefbbeb5,0x3efb3eb5,0x3dc8beb5,0x3ed53eed,0x3e8ebe44,0xbe8e3e44,0x3ed53eed,
0xbea2bf00,0xbec60000,0x3d49beb5,0xbeffbeb5,0x3ee23dc8,0xbe71befb,0x3ef53ed5,0x3e15be8e,0x3e153eed,0x3ef53e44,0xbe713e44,0x3ee23eed,0xbeffbe8e,0x3d493ed5,0xbec6befb,0xbea23dc8,
0x3f003f00,0xbf003f00,0x3f003f00,0xbf003f00,0x3f003f00,0xbf003f00,0x3f003f00,0xbf003f00,0x3f003f00,0xbf003f00,0x3f003f00,0xbf003f00,0x3f003f00,0xbf003f00,0x3f003f00,0xbf003f00,
0x3d490000,0x3eff3f00,0x3ec63eb5,0x3ea23eb5,0x3e153dc8,0x3ef53efb,0x3ee23ed5,0x3e713e8e,0x3e713e44,0x3ee23eed,0x3ef53eed,0x3e153e44,0x3ea23e8e,0x3ec63ed5,0x3eff3efb,0x3d493dc8,
0xbefbbf00,0x3dc80000,0x3dc80000,0x3efb3f00,0xbed5beed,0x3e8e3e44,0x3e8e3e44,0x3ed53eed,0xbe8ebeb5,0x3ed53eb5,0x3ed53eb5,0x3e8e3eb5,0xbdc8be44,0x3efb3eed,0x3efb3eed,0x3dc83e44,
0xbe150000,0xbef5bf00,0xbe71beb5,0x3ee23eb5,0xbec6be8e,0xbea2bed5,0x3d49bdc8,0x3eff3efb,0xbeffbeed,0xbd49be44,0x3ea23e44,0x3ec63eed,0xbee2befb,0x3e713dc8,0x3ef53ed5,0x3e153e8e,
0x3eed3f00,0xbe440000,0xbeedbf00,0x3e440000,0x3e443eb5,0xbeedbeb5,0xbe44beb5,0x3eed3eb5,0xbe440000,0xbeedbf00,0x3e440000,0x3eed3f00,0xbeedbeb5,0xbe44beb5,0x3eed3eb5,0x3e443eb5,
0x3e710000,0x3ee23f00,0xbef5beb5,0xbe15beb5,0x3eff3ed5,0x3d493e8e,0xbec6befb,0x3ea23dc8,0x3ea23eed,0xbec6be44,0x3d49be44,0x3eff3eed,0xbe153dc8,0xbef5befb,0x3ee23e8e,0x3e713ed5,
0xbed5bf00,0x3e8e0000,0xbe8e0000,0xbed5bf00,0x3dc8be44,0x3efb3eed,0xbefbbeed,0x3dc8be44,0x3efb3eb5,0x3dc83eb5,0xbdc8beb5,0x3efb3eb5,0x3e8e3eed,0xbed5be44,0x3ed53e44,0x3e8e3eed,
0xbea20000,0xbec6bf00,0x3d493eb5,0xbeffbeb5,0xbee2befb,0x3e71bdc8,0xbef5be8e,0xbe15bed5,0x3e15be44,0x3ef53eed,0xbe71beed,0x3ee23e44,0x3eff3ed5,0xbd493e8e,0x3ec63dc8,0x3ea23efb,
0x3f00,0xbf000000,0x3f00,0xbf000000,0xbf00,0x3f000000,0xbf00,0x3f000000,0x3f00,0xbf000000,0x3f00,0xbf000000,0xbf00,0x3f000000,0xbf00,0x3f000000,
0x3eff0000,0xbd493f00,0x3ea23eb5,0xbec63eb5,0xbef5bdc8,0x3e15befb,0xbe71bed5,0x3ee2be8e,0x3ee23e44,0xbe713eed,0x3e153eed,0xbef53e44,0xbec6be8e,0x3ea2bed5,0xbd49befb,0x3effbdc8,
0x3dc8bf00,0x3efb0000,0x3efb0000,0xbdc83f00,0xbe8e3eed,0xbed5be44,0xbed5be44,0x3e8ebeed,0x3ed5beb5,0x3e8e3eb5,0x3e8e3eb5,0xbed53eb5,0xbefb3e44,0xbdc8beed,0xbdc8beed,0x3efbbe44,
0xbef50000,0x3e15bf00,0x3ee2beb5,0x3e713eb5,0x3ea23e8e,0xbec63ed5,0xbeff3dc8,0x3d49befb,0xbd49beed,0x3effbe44,0x3ec63e44,0xbea23eed,0xbe713efb,0xbee2bdc8,0xbe15bed5,0x3ef5be8e,
0xbe443f00,0xbeed0000,0x3e44bf00,0x3eed0000,0x3eedbeb5,0x3e443eb5,0xbeed3eb5,0xbe44beb5,0xbeed0000,0x3e44bf00,0x3eed0000,0xbe443f00,0x3e443eb5,0xbeed3eb5,0xbe44beb5,0x3eedbeb5,
0x3ee20000,0xbe713f00,0xbe15beb5,0x3ef5beb5,0xbd49bed5,0x3effbe8e,0xbea23efb,0xbec6bdc8,0xbec63eed,0xbea2be44,0x3effbe44,0xbd493eed,0x3ef5bdc8,0xbe153efb,0xbe71be8e,0x3ee2bed5,
0x3e8ebf00,0x3ed50000,0xbed50000,0x3e8ebf00,0xbefb3e44,0x3dc8beed,0xbdc83eed,0xbefb3e44,0x3dc83eb5,0xbefb3eb5,0x3efbbeb5,0x3dc83eb5,0x3ed5beed,0x3e8e3e44,0xbe8ebe44,0x3ed5beed,
0xbec60000,0x3ea2bf00,0xbeff3eb5,0xbd49beb5,0xbe713efb,0xbee23dc8,0x3e153e8e,0xbef53ed5,0x3ef5be44,0xbe153eed,0x3ee2beed,0x3e713e44,0x3d49bed5,0x3effbe8e,0xbea2bdc8,0x3ec6befb,
0x3eb53f00,0xbeb50000,0x3eb53f00,0xbeb50000,0xbeb50000,0xbeb5bf00,0xbeb50000,0xbeb5bf00,0xbeb5bf00,0x3eb50000,0xbeb5bf00,0x3eb50000,0x3eb50000,0x3eb53f00,0x3eb50000,0x3eb53f00,
0xbd490000,0xbeff3f00,0xbec63eb5,0xbea23eb5,0xbe153dc8,0xbef53efb,0xbee23ed5,0xbe713e8e,0xbe713e44,0xbee23eed,0xbef53eed,0xbe153e44,0xbea23e8e,0xbec63ed5,0xbeff3efb,0xbd493dc8,
0x3efbbf00,0xbdc80000,0xbdc80000,0xbefb3f00,0x3ed5beed,0xbe8e3e44,0xbe8e3e44,0xbed53eed,0x3e8ebeb5,0xbed53eb5,0xbed53eb5,0xbe8e3eb5,0x3dc8be44,0xbefb3eed,0xbefb3eed,0xbdc83e44,
0x3e150000,0x3ef5bf00,0x3e71beb5,0xbee23eb5,0x3ec6be8e,0x3ea2bed5,0xbd49bdc8,0xbeff3efb,0x3effbeed,0x3d49be44,0xbea23e44,0xbec63eed,0x3ee2befb,0xbe713dc8,0xbef53ed5,0xbe153e8e,
0xbeed3f00,0x3e440000,0x3eedbf00,0xbe440000,0xbe443eb5,0x3eedbeb5,0x3e44beb5,0xbeed3eb5,0x3e440000,0x3eedbf00,0xbe440000,0xbeed3f00,0x3eedbeb5,0x3e44beb5,0xbeed3eb5,0xbe443eb5,
0xbe710000,0xbee23f00,0x3ef5beb5,0x3e15beb5,0xbeff3ed5,0xbd493e8e,0x3ec6befb,0xbea23dc8,0xbea23eed,0x3ec6be44,0xbd49be44,0xbeff3eed,0x3e153dc8,0x3ef5befb,0xbee23e8e,0xbe713ed5,
0x3ed5bf00,0xbe8e0000,0x3e8e0000,0x3ed5bf00,0xbdc8be44,0xbefb3eed,0x3efbbeed,0xbdc8be44,0xbefb3eb5,0xbdc83eb5,0x3dc8beb5,0xbefb3eb5,0xbe8e3eed,0x3ed5be44,0xbed53e44,0xbe8e3eed,
0x3ea20000,0x3ec6bf00,0xbd493eb5,0x3effbeb5,0x3ee2befb,0xbe71bdc8,0x3ef5be8e,0x3e15bed5,0xbe15be44,0xbef53eed,0x3e71beed,0xbee23e44,0xbeff3ed5,0x3d493e8e,0xbec63dc8,0xbea23efb,
0xbeb53f00,0xbeb50000,0xbeb53f00,0xbeb50000,0x3eb50000,0xbeb53f00,0x3eb50000,0xbeb53f00,0x3eb5bf00,0x3eb50000,0x3eb5bf00,0x3eb50000,0xbeb50000,0x3eb5bf00,0xbeb50000,0x3eb5bf00,
0xbeff0000,0x3d493f00,0xbea23eb5,0x3ec63eb5,0x3ef5bdc8,0xbe15befb,0x3e71bed5,0xbee2be8e,0xbee23e44,0x3e713eed,0xbe153eed,0x3ef53e44,0x3ec6be8e,0xbea2bed5,0x3d49befb,0xbeffbdc8,
0xbdc8bf00,0xbefb0000,0xbefb0000,0x3dc83f00,0x3e8e3eed,0x3ed5be44,0x3ed5be44,0xbe8ebeed,0xbed5beb5,0xbe8e3eb5,0xbe8e3eb5,0x3ed53eb5,0x3efb3e44,0x3dc8beed,0x3dc8beed,0xbefbbe44,
0x3ef50000,0xbe15bf00,0xbee2beb5,0xbe713eb5,0xbea23e8e,0x3ec63ed5,0x3eff3dc8,0xbd49befb,0x3d49beed,0xbeffbe44,0xbec63e44,0x3ea23eed,0x3e713efb,0x3ee2bdc8,0x3e15bed5,0xbef5be8e,
0x3e443f00,0x3eed0000,0xbe44bf00,0xbeed0000,0xbeedbeb5,0xbe443eb5,0x3eed3eb5,0x3e44beb5,0x3eed0000,0xbe44bf00,0xbeed0000,0x3e443f00,0xbe443eb5,0x3eed3eb5,0x3e44beb5,0xbeedbeb5,
0xbee20000,0x3e713f00,0x3e15beb5,0xbef5beb5,0x3d49bed5,0xbeffbe8e,0x3ea23efb,0x3ec6bdc8,0x3ec63eed,0x3ea2be44,0xbeffbe44,0x3d493eed,0xbef5bdc8,0x3e153efb,0x3e71be8e,0xbee2bed5,
0xbe8ebf00,0xbed50000,0x3ed50000,0xbe8ebf00,0x3efb3e44,0xbdc8beed,0x3dc83eed,0x3efb3e44,0xbdc83eb5,0x3efb3eb5,0xbefbbeb5,0xbdc83eb5,0xbed5beed,0xbe8e3e44,0x3e8ebe44,0xbed5beed,
0x3ec60000,0xbea2bf00,0x3eff3eb5,0x3d49beb5,0x3e713efb,0x3ee23dc8,0xbe153e8e,0x3ef53ed5,0xbef5be44,0x3e153eed,0xbee2beed,0xbe713e44,0xbd49bed5,0xbeffbe8e,0x3ea2bdc8,0xbec6befb,
0x3f800000,0x0,0x3f800000,0x0,0x3f800000,0x0,0x3f800000,0x0,0x3f800000,0x0,0x3f800000,0x0,0x3f800000,0x0,0x3f800000,0x0,
0x3f800000,0x0,0x3f7fec43,0xbcc90ab0,0x3f7fb10f,0xbd48fb30,0x3f7f4e6d,0xbd96a905,0x3f7ec46d,0xbdc8bd36,0x3f7e1324,0xbdfab273,0x3f7d3aac,0xbe164083,0x3f7c3b28,0xbe2f10a2,
0x3f800000,0x0,0x3f7ffec4,0xbbc90f88,0x3f7ffb11,0xbc490e90,0x3f7ff4e6,0xbc96c9b6,0x3f7fec43,0xbcc90ab0,0x3f7fe129,0xbcfb49ba,0x3f7fd397,0xbd16c32c,0x3f7fc38f,0xbd2fe007,
0x3f800000,0x0,0x3f7fe129,0xbcfb49ba,0x3f7f84ab,0xbd7b2b74,0x3f7eea9d,0xbdbc3ac3,0x3f7e1324,0xbdfab273,0x3f7cfe73,0xbe1c76de,0x3f7baccd,0xbe3b6ecf,0x3f7a1e84,0xbe5a3997,
0x3f800000,0x0,0x3f7ffb11,0xbc490e90,0x3f7fec43,0xbcc90ab0,0x3f7fd397,0xbd16c32c,0x3f7fb10f,0xbd48fb30,0x3f7f84ab,0xbd7b2b74,0x3f7f4e6d,0xbd96a905,0x3f7f0e58,0xbdafb680,
0x3f800000,0x0,0x3f7fd397,0xbd16c32c,0x3f7f4e6d,0xbd96a905,0x3f7e70b0,0xbde1bc2e,0x3f7d3aac,0xbe164083,0x3f7baccd,0xbe3b6ecf,0x3f79c79d,0xbe605c13,0x3f778bc5,0xbe827dc0,
0x3f800000,0x0,0x3f7ff4e6,0xbc96c9b6,0x3f7fd397,0xbd16c32c,0x3f7f9c18,0xbd621469,0x3f7f4e6d,0xbd96a905,0x3f7eea9d,0xbdbc3ac3,0x3f7e70b0,0xbde1bc2e,0x3f7de0b1,0xbe039502,
0x3f800000,0x0,0x3f7fc38f,0xbd2fe007,0x3f7f0e58,0xbdafb680,0x3f7de0b1,0xbe039502,0x3f7c3b28,0xbe2f10a2,0x3f7a1e84,0xbe5a3997,0x3f778bc5,0xbe827dc0,0x3f748422,0xbe97a117,
0x3f800000,0x0,0x3f7fb10f,0xbd48fb30,0x3f7ec46d,0xbdc8bd36,0x3f7d3aac,0xbe164083,0x3f7b14be,0xbe47c5c2,0x3f7853f8,0xbe78cfcc,0x3f74fa0b,0xbe94a031,0x3f710908,0xbeac7cd4,
0x3f800000,0x0,0x3f7f4e6d,0xbd96a905,0x3f7d3aac,0xbe164083,0x3f79c79d,0xbe605c13,0x3f74fa0b,0xbe94a031,0x3f6ed89e,0xbeb8442a,0x3f676bd8,0xbedae880,0x3f5ebe05,0xbefc5d27,
0x3f800000,0x0,0x3f7f9c18,0xbd621469,0x3f7e70b0,0xbde1bc2e,0x3f7c7eb0,0xbe28defc,0x3f79c79d,0xbe605c13,0x3f764d97,0xbe8b9507,0x3f721352,0xbea68f12,0x3f6d1c1d,0xbec1071e,
0x3f800000,0x0,0x3f7f2f9d,0xbda3308c,0x3f7cbfc9,0xbe22abb6,0x3f78b47b,0xbe72b651,0x3f731447,0xbea09ae5,0x3f6be858,0xbec6d529,0x3f633c5a,0xbeebcbbb,0x3f591e6a,0xbf07a136,
0x3f800000,0x0,0x3f7f84ab,0xbd7b2b74,0x3f7e1324,0xbdfab273,0x3f7baccd,0xbe3b6ecf,0x3f7853f8,0xbe78cfcc,0x3f740bdd,0xbe9aa086,0x3f6ed89e,0xbeb8442a,0x3f68bf3c,0xbed53641,
0x3f800000,0x0,0x3f7f0e58,0xbdafb680,0x3f7c3b28,0xbe2f10a2,0x3f778bc5,0xbe827dc0,0x3f710908,0xbeac7cd4,0x3f68bf3c,0xbed53641,0x3f5ebe05,0xbefc5d27,0x3f531849,0xbf10d3cd,
0x3f800000,0x0,0x3f7f6ac7,0xbd8a200a,0x3f7dabcc,0xbe09cf86,0x3f7ac516,0xbe4dee60,0x3f76ba07,0xbe888e93,0x3f718f57,0xbea986c4,0x3f6b4b0c,0xbec9b953,0x3f63f473,0xbee900b7,
0x3f800000,0x0,0x3f7eea9d,0xbdbc3ac3,0x3f7baccd,0xbe3b6ecf,0x3f764d97,0xbe8b9507,0x3f6ed89e,0xbeb8442a,0x3f655e0b,0xbee363fa,0x3f59f26a,0xbf064b82,0x3f4cae79,0xbf19c200,
0x3f800000,0x0,0x3f7ec46d,0xbdc8bd36,0x3f7b14be,0xbe47c5c2,0x3f74fa0b,0xbe94a031,0x3f6c835e,0xbec3ef15,0x3f61c598,0xbef15aea,0x3f54db31,0xbf0e39da,0x3f45e403,0xbf226799,
0x3f800000,0x0,0x3f7e1324,0xbdfab273,0x3f7853f8,0xbe78cfcc,0x3f6ed89e,0xbeb8442a,0x3f61c598,0xbef15aea,0x3f514d3d,0xbf13682a,0x3f3daef9,0xbf2beb4a,0x3f273656,0xbf41d870,
0x3f800000,0x0,0x3f7e9bc9,0xbdd53db9,0x3f7a7302,0xbe541501,0x3f73913f,0xbe9d9e78,0x3f6a09a7,0xbecf7bca,0x3f5df6be,0xbeff17b2,0x3f4f7a1f,0xbf15f6d9,0x3f3ebc1b,0xbf2ac082,
0x3f800000,0x0,0x3f7de0b1,0xbe039502,0x3f778bc5,0xbe827dc0,0x3f6d1c1d,0xbec1071e,0x3f5ebe05,0xbefc5d27,0x3f4cae79,0xbf19c200,0x3f373a23,0xbf32c8c9,0x3f1ebc12,0xbf48d8b3,
0x3f800000,0x0,0x3f7e70b0,0xbde1bc2e,0x3f79c79d,0xbe605c13,0x3f721352,0xbea68f12,0x3f676bd8,0xbedae880,0x3f59f26a,0xbf064b82,0x3f49d112,0xbf1d7fd1,0x3f373a23,0xbf32c8c9,
0x3f800000,0x0,0x3f7dabcc,0xbe09cf86,0x3f76ba07,0xbe888e93,0x3f6b4b0c,0xbec9b953,0x3f5b941a,0xbf039c3d,0x3f47de65,0xbf1ff6cb,0x3f3085bb,0xbf396842,0x3f15f6d9,0xbf4f7a1f,
0x3f800000,0x0,0x3f7e4323,0xbdee3876,0x3f791298,0xbe6c9a7f,0x3f708066,0xbeaf713a,0x3f64aa59,0xbee63375,0x3f55b993,0xbf0cead0,0x3f43e200,0xbf24d225,0x3f2f61a5,0xbf3a7ca4,
0x3f800000,0x0,0x3f7d7474,0xbe1008b7,0x3f75dec6,0xbe8e9a22,0x3f696591,0xbed25a09,0x3f584853,0xbf08f59b,0x3f42de29,0xbf26050a,0x3f299415,0xbf3fc767,0x3f0cead0,0xbf55b993,
0x3f800000,0x0,0x3f7d3aac,0xbe164083,0x3f74fa0b,0xbe94a031,0x3f676bd8,0xbedae880,0x3f54db31,0xbf0e39da,0x3f3daef9,0xbf2beb4a,0x3f226799,0xbf45e403,0x3f039c3d,0xbf5b941a,
0x3f800000,0x0,0x3f7c3b28,0xbe2f10a2,0x3f710908,0xbeac7cd4,0x3f5ebe05,0xbefc5d27,0x3f45e403,0xbf226799,0x3f273656,0xbf41d870,0x3f039c3d,0xbf5b941a,0x3eb8442a,0xbf6ed89e,
0x3f800000,0x0,0x3f7cfe73,0xbe1c76de,0x3f740bdd,0xbe9aa086,0x3f655e0b,0xbee363fa,0x3f514d3d,0xbf13682a,0x3f385216,0xbf31a81d,0x3f1b02c6,0xbf4bbbf8,0x3ef41f07,0xbf6106f2,
0x3f800000,0x0,0x3f7bf531,0xbe354098,0x3f6ff573,0xbeb263ef,0x3f5c61c7,0xbf0242b1,0x3f41d870,0xbf273656,0x3f212ff9,0xbf46e22a,0x3ef6e0cb,0xbf604621,0x3ea395c5,0xbf7294f8,
0x3f800000,0x0,0x3f7cbfc9,0xbe22abb6,0x3f731447,0xbea09ae5,0x3f633c5a,0xbeebcbbb,0x3f4d9f02,0xbf187fc0,0x3f32c8c9,0xbf373a23,0x3f13682a,0xbf514d3d,0x3ee0924f,0xbf660f88,
0x3f800000,0x0,0x3f7baccd,0xbe3b6ecf,0x3f6ed89e,0xbeb8442a,0x3f59f26a,0xbf064b82,0x3f3daef9,0xbf2beb4a,0x3f1b02c6,0xbf4bbbf8,0x3ee63375,0xbf64aa59,0x3e8e9a22,0xbf75dec6,
0x3f800000,0x0,0x3f7c7eb0,0xbe28defc,0x3f721352,0xbea68f12,0x3f6106f2,0xbef41f07,0x3f49d112,0xbf1d7fd1,0x3f2d1469,0xbf3ca003,0x3f0b9a6b,0xbf5695e5,0x3ecc9b8b,0xbf6aab7b,
0x3f800000,0x0,0x3f7b61fc,0xbe419b37,0x3f6db293,0xbebe1d4a,0x3f577026,0xbf0a48ad,0x3f396842,0xbf3085bb,0x3f14b039,0xbf5064af,0x3ed53641,0xbf68bf3c,0x3e72b651,0xbf78b47b,
0x3f800000,0x0,0x3f800000,0x0,0x3f800000,0x0,0x3f800000,0x0,0x3f800000,0x0,0x3f800000,0x0,0x3f800000,0x0,0x3f800000,0x0,
0x3f7b14be,0xbe47c5c2,0x3f79c79d,0xbe605c13,0x3f7853f8,0xbe78cfcc,0x3f76ba07,0xbe888e93,0x3f74fa0b,0xbe94a031,0x3f731447,0xbea09ae5,0x3f710908,0xbeac7cd4,0x3f6ed89e,0xbeb8442a,
0x3f7fb10f,0xbd48fb30,0x3f7f9c18,0xbd621469,0x3f7f84ab,0xbd7b2b74,0x3f7f6ac7,0xbd8a200a,0x3f7f4e6d,0xbd96a905,0x3f7f2f9d,0xbda3308c,0x3f7f0e58,0xbdafb680,0x3f7eea9d,0xbdbc3ac3,
0x3f7853f8,0xbe78cfcc,0x3f764d97,0xbe8b9507,0x3f740bdd,0xbe9aa086,0x3f718f57,0xbea986c4,0x3f6ed89e,0xbeb8442a,0x3f6be858,0xbec6d529,0x3f68bf3c,0xbed53641,0x3f655e0b,0xbee363fa,
0x3f7ec46d,0xbdc8bd36,0x3f7e70b0,0xbde1bc2e,0x3f7e1324,0xbdfab273,0x3f7dabcc,0xbe09cf86,0x3f7d3aac,0xbe164083,0x3f7cbfc9,0xbe22abb6,0x3f7c3b28,0xbe2f10a2,0x3f7baccd,0xbe3b6ecf,
0x3f74fa0b,0xbe94a031,0x3f721352,0xbea68f12,0x3f6ed89e,0xbeb8442a,0x3f6b4b0c,0xbec9b953,0x3f676bd8,0xbedae880,0x3f633c5a,0xbeebcbbb,0x3f5ebe05,0xbefc5d27,0x3f59f26a,0xbf064b82,
0x3f7d3aac,0xbe164083,0x3f7c7eb0,0xbe28defc,0x3f7baccd,0xbe3b6ecf,0x3f7ac516,0xbe4dee60,0x3f79c79d,0xbe605c13,0x3f78b47b,0xbe72b651,0x3f778bc5,0xbe827dc0,0x3f764d97,0xbe8b9507,
0x3f710908,0xbeac7cd4,0x3f6d1c1d,0xbec1071e,0x3f68bf3c,0xbed53641,0x3f63f473,0xbee900b7,0x3f5ebe05,0xbefc5d27,0x3f591e6a,0xbf07a136,0x3f531849,0xbf10d3cd,0x3f4cae79,0xbf19c200,
0x3f6c835e,0xbec3ef15,0x3f676bd8,0xbedae880,0x3f61c598,0xbef15aea,0x3f5b941a,0xbf039c3d,0x3f54db31,0xbf0e39da,0x3f4d9f02,0xbf187fc0,0x3f45e403,0xbf226799,0x3f3daef9,0xbf2beb4a,
0x3f54db31,0xbf0e39da,0x3f49d112,0xbf1d7fd1,0x3f3daef9,0xbf2beb4a,0x3f3085bb,0xbf396842,0x3f226799,0xbf45e403,0x3f13682a,0xbf514d3d,0x3f039c3d,0xbf5b941a,0x3ee63375,0xbf64aa59,
0x3f676bd8,0xbedae880,0x3f6106f2,0xbef41f07,0x3f59f26a,0xbf064b82,0x3f5233c6,0xbf121eb0,0x3f49d112,0xbf1d7fd1,0x3f40d0da,0xbf286605,0x3f373a23,0xbf32c8c9,0x3f2d1469,0xbf3ca003,
0x3f4d9f02,0xbf187fc0,0x3f40d0da,0xbf286605,0x3f32c8c9,0xbf373a23,0x3f239da9,0xbf44e3f5,0x3f13682a,0xbf514d3d,0x3f0242b1,0xbf5c61c7,0x3ee0924f,0xbf660f88,0x3ebb31a0,0xbf6e46be,
0x3f61c598,0xbef15aea,0x3f59f26a,0xbf064b82,0x3f514d3d,0xbf13682a,0x3f47de65,0xbf1ff6cb,0x3f3daef9,0xbf2beb4a,0x3f32c8c9,0xbf373a23,0x3f273656,0xbf41d870,0x3f1b02c6,0xbf4bbbf8,
0x3f45e403,0xbf226799,0x3f373a23,0xbf32c8c9,0x3f273656,0xbf41d870,0x3f15f6d9,0xbf4f7a1f,0x3f039c3d,0xbf5b941a,0x3ee0924f,0xbf660f88,0x3eb8442a,0xbf6ed89e,0x3e8e9a22,0xbf75dec6,
0x3f5b941a,0xbf039c3d,0x3f5233c6,0xbf121eb0,0x3f47de65,0xbf1ff6cb,0x3f3ca003,0xbf2d1469,0x3f3085bb,0xbf396842,0x3f239da9,0xbf44e3f5,0x3f15f6d9,0xbf4f7a1f,0x3f07a136,0xbf591e6a,
0x3f3daef9,0xbf2beb4a,0x3f2d1469,0xbf3ca003,0x3f1b02c6,0xbf4bbbf8,0x3f07a136,0xbf591e6a,0x3ee63375,0xbf64aa59,0x3ebb31a0,0xbf6e46be,0x3e8e9a22,0xbf75dec6,0x3e419b37,0xbf7b61fc,
0x3f3504f3,0xbf3504f3,0x3f226799,0xbf45e403,0x3f0e39da,0xbf54db31,0x3ef15aea,0xbf61c598,0x3ec3ef15,0xbf6c835e,0x3e94a031,0xbf74fa0b,0x3e47c5c2,0xbf7b14be,0x3dc8bd36,0xbf7ec46d,
0x3f0e39da,0xbf54db31,0x3ee63375,0xbf64aa59,0x3eac7cd4,0xbf710908,0x3e605c13,0xbf79c79d,0x3dc8bd36,0xbf7ec46d,0xbcc90ab0,0xbf7fec43,0xbe164083,0xbf7d3aac,0xbe888e93,0xbf76ba07,
0x3f2beb4a,0xbf3daef9,0x3f173c07,0xbf4e8d90,0x3f00e7e4,0xbf5d2d53,0x3ed25a09,0xbf696591,0x3ea09ae5,0xbf731447,0x3e5a3997,0xbf7a1e84,0x3de1bc2e,0xbf7e70b0,0x3bc90f88,0xbf7ffec4,
0x3f039c3d,0xbf5b941a,0x3ecc9b8b,0xbf6aab7b,0x3e8e9a22,0xbf75dec6,0x3e1c76de,0xbf7cfe73,0x3cc90ab0,0xbf7fec43,0xbdd53db9,0xbf7e9bc9,0xbe6c9a7f,0xbf791298,0xbeb554ec,0xbf6f6830,
0x3f226799,0xbf45e403,0x3f0b9a6b,0xbf5695e5,0x3ee63375,0xbf64aa59,0x3eb263ef,0xbf6ff573,0x3e78cfcc,0xbf7853f8,0x3e09cf86,0xbf7dabcc,0x3cc90ab0,0xbf7fec43,0xbdafb680,0xbf7f0e58,
0x3ef15aea,0xbf61c598,0x3eb263ef,0xbf6ff573,0x3e605c13,0xbf79c79d,0x3dafb680,0xbf7f0e58,0xbd48fb30,0xbf7fb10f,0xbe3b6ecf,0xbf7baccd,0xbea09ae5,0xbf731447,0xbee0924f,0xbf660f88,
0x3f187fc0,0xbf4d9f02,0x3eff17b2,0xbf5df6be,0x3ec9b953,0xbf6b4b0c,0x3e919ddd,0xbf756d97,0x3e2f10a2,0xbf7c3b28,0x3d621469,0xbf7f9c18,0xbd7b2b74,0xbf7f84ab,0xbe354098,0xbf7bf531,
0x3edae880,0xbf676bd8,0x3e97a117,0xbf748422,0x3e22abb6,0xbf7cbfc9,0x3c96c9b6,0xbf7ff4e6,0xbdfab273,0xbf7e1324,0xbe8586ce,0xbf772417,0xbec9b953,0xbf6b4b0c,0xbf04f484,0xbf5ac450,
0x3ec3ef15,0xbf6c835e,0x3e78cfcc,0xbf7853f8,0x3dc8bd36,0xbf7ec46d,0xbd48fb30,0xbf7fb10f,0xbe47c5c2,0xbf7b14be,0xbeac7cd4,0xbf710908,0xbef15aea,0xbf61c598,0xbf187fc0,0xbf4d9f02,
0x3e47c5c2,0xbf7b14be,0x3cc90ab0,0xbf7fec43,0xbe164083,0xbf7d3aac,0xbea09ae5,0xbf731447,0xbef15aea,0xbf61c598,0xbf1d7fd1,0xbf49d112,0xbf3daef9,0xbf2beb4a,0xbf584853,0xbf08f59b,
0x3eac7cd4,0xbf710908,0x3e419b37,0xbf7b61fc,0x3d16c32c,0xbf7fd397,0xbdee3876,0xbf7e4323,0xbe888e93,0xbf76ba07,0xbed25a09,0xbf696591,0xbf0b9a6b,0xbf5695e5,0xbf2ac082,0xbf3ebc1b,
0x3e164083,0xbf7d3aac,0xbcfb49ba,0xbf7fe129,0xbe541501,0xbf7a7302,0xbec1071e,0xbf6d1c1d,0xbf08f59b,0xbf584853,0xbf2d1469,0xbf3ca003,0xbf4bbbf8,0xbf1b02c6,0xbf63f473,0xbee900b7,
0x3e94a031,0xbf74fa0b,0x3e09cf86,0xbf7dabcc,0xbcc90ab0,0xbf7fec43,0xbe3b6ecf,0xbf7baccd,0xbeac7cd4,0xbf710908,0xbef6e0cb,0xbf604621,0xbf1d7fd1,0xbf49d112,0xbf3b8f3b,0xbf2e3bde,
0x3dc8bd36,0xbf7ec46d,0xbdafb680,0xbf7f0e58,0xbe888e93,0xbf76ba07,0xbee0924f,0xbf660f88,0xbf187fc0,0xbf4d9f02,0xbf3b8f3b,0xbf2e3bde,0xbf584853,0xbf08f59b,0xbf6db293,0xbebe1d4a,
0x3e78cfcc,0xbf7853f8,0x3da3308c,0xbf7f2f9d,0xbdafb680,0xbf7f0e58,0xbe7ee6e1,0xbf77f110,0xbecf7bca,0xbf6a09a7,0xbf0cead0,0xbf55b993,0xbf2e3bde,0xbf3b8f3b,0xbf4ac77f,0xbf1c420c,
0x3d48fb30,0xbf7fb10f,0xbe1008b7,0xbf7d7474,0xbea68f12,0xbf721352,0xbeff17b2,0xbf5df6be,0xbf273656,0xbf41d870,0xbf48d8b3,0xbf1ebc12,0xbf633c5a,0xbeebcbbb,0xbf756d97,0xbe919ddd,
0x3f800000,0x0,0x3f800000,0x0,0x3f800000,0x0,0x3f800000,0x0,0x3f800000,0x0,0x3f800000,0x0,0x3f800000,0x0,0x3f800000,0x0,
0x3f6c835e,0xbec3ef15,0x3f6a09a7,0xbecf7bca,0x3f676bd8,0xbedae880,0x3f64aa59,0xbee63375,0x3f61c598,0xbef15aea,0x3f5ebe05,0xbefc5d27,0x3f5b941a,0xbf039c3d,0x3f584853,0xbf08f59b,
0x3f7ec46d,0xbdc8bd36,0x3f7e9bc9,0xbdd53db9,0x3f7e70b0,0xbde1bc2e,0x3f7e4323,0xbdee3876,0x3f7e1324,0xbdfab273,0x3f7de0b1,0xbe039502,0x3f7dabcc,0xbe09cf86,0x3f7d7474,0xbe1008b7,
0x3f61c598,0xbef15aea,0x3f5df6be,0xbeff17b2,0x3f59f26a,0xbf064b82,0x3f55b993,0xbf0cead0,0x3f514d3d,0xbf13682a,0x3f4cae79,0xbf19c200,0x3f47de65,0xbf1ff6cb,0x3f42de29,0xbf26050a,
0x3f7b14be,0xbe47c5c2,0x3f7a7302,0xbe541501,0x3f79c79d,0xbe605c13,0x3f791298,0xbe6c9a7f,0x3f7853f8,0xbe78cfcc,0x3f778bc5,0xbe827dc0,0x3f76ba07,0xbe888e93,0x3f75dec6,0xbe8e9a22,
0x3f54db31,0xbf0e39da,0x3f4f7a1f,0xbf15f6d9,0x3f49d112,0xbf1d7fd1,0x3f43e200,0xbf24d225,0x3f3daef9,0xbf2beb4a,0x3f373a23,0xbf32c8c9,0x3f3085bb,0xbf396842,0x3f299415,0xbf3fc767,
0x3f74fa0b,0xbe94a031,0x3f73913f,0xbe9d9e78,0x3f721352,0xbea68f12,0x3f708066,0xbeaf713a,0x3f6ed89e,0xbeb8442a,0x3f6d1c1d,0xbec1071e,0x3f6b4b0c,0xbec9b953,0x3f696591,0xbed25a09,
0x3f45e403,0xbf226799,0x3f3ebc1b,0xbf2ac082,0x3f373a23,0xbf32c8c9,0x3f2f61a5,0xbf3a7ca4,0x3f273656,0xbf41d870,0x3f1ebc12,0xbf48d8b3,0x3f15f6d9,0xbf4f7a1f,0x3f0cead0,0xbf55b993,
0x3f3504f3,0xbf3504f3,0x3f2beb4a,0xbf3daef9,0x3f226799,0xbf45e403,0x3f187fc0,0xbf4d9f02,0x3f0e39da,0xbf54db31,0x3f039c3d,0xbf5b941a,0x3ef15aea,0xbf61c598,0x3edae880,0xbf676bd8,
0x3ec3ef15,0xbf6c835e,0x3ea09ae5,0xbf731447,0x3e78cfcc,0xbf7853f8,0x3e2f10a2,0xbf7c3b28,0x3dc8bd36,0xbf7ec46d,0x3cc90ab0,0xbf7fec43,0xbd48fb30,0xbf7fb10f,0xbdfab273,0xbf7e1324,
0x3f226799,0xbf45e403,0x3f173c07,0xbf4e8d90,0x3f0b9a6b,0xbf5695e5,0x3eff17b2,0xbf5df6be,0x3ee63375,0xbf64aa59,0x3ecc9b8b,0xbf6aab7b,0x3eb263ef,0xbf6ff573,0x3e97a117,0xbf748422,
0x3e94a031,0xbf74fa0b,0x3e5a3997,0xbf7a1e84,0x3e09cf86,0xbf7dabcc,0x3d621469,0xbf7f9c18,0xbcc90ab0,0xbf7fec43,0xbdd53db9,0xbf7e9bc9,0xbe3b6ecf,0xbf7baccd,0xbe8586ce,0xbf772417,
0x3f0e39da,0xbf54db31,0x3f00e7e4,0xbf5d2d53,0x3ee63375,0xbf64aa59,0x3ec9b953,0xbf6b4b0c,0x3eac7cd4,0xbf710908,0x3e8e9a22,0xbf75dec6,0x3e605c13,0xbf79c79d,0x3e22abb6,0xbf7cbfc9,
0x3e47c5c2,0xbf7b14be,0x3de1bc2e,0xbf7e70b0,0x3cc90ab0,0xbf7fec43,0xbd7b2b74,0xbf7f84ab,0xbe164083,0xbf7d3aac,0xbe6c9a7f,0xbf791298,0xbea09ae5,0xbf731447,0xbec9b953,0xbf6b4b0c,
0x3ef15aea,0xbf61c598,0x3ed25a09,0xbf696591,0x3eb263ef,0xbf6ff573,0x3e919ddd,0xbf756d97,0x3e605c13,0xbf79c79d,0x3e1c76de,0xbf7cfe73,0x3dafb680,0xbf7f0e58,0x3c96c9b6,0xbf7ff4e6,
0x3dc8bd36,0xbf7ec46d,0x3bc90f88,0xbf7ffec4,0xbdafb680,0xbf7f0e58,0xbe354098,0xbf7bf531,0xbe888e93,0xbf76ba07,0xbeb554ec,0xbf6f6830,0xbee0924f,0xbf660f88,0xbf04f484,0xbf5ac450,
0x0,0xbf800000,0xbdc8bd36,0xbf7ec46d,0xbe47c5c2,0xbf7b14be,0xbe94a031,0xbf74fa0b,0xbec3ef15,0xbf6c835e,0xbef15aea,0xbf61c598,0xbf0e39da,0xbf54db31,0xbf226799,0xbf45e403,
0xbec3ef15,0xbf6c835e,0xbefc5d27,0xbf5ebe05,0xbf187fc0,0xbf4d9f02,0xbf3085bb,0xbf396842,0xbf45e403,0xbf226799,0xbf584853,0xbf08f59b,0xbf676bd8,0xbedae880,0xbf731447,0xbea09ae5,
0xbdc8bd36,0xbf7ec46d,0xbe4dee60,0xbf7ac516,0xbe9aa086,0xbf740bdd,0xbecc9b8b,0xbf6aab7b,0xbefc5d27,0xbf5ebe05,0xbf14b039,0xbf5064af,0xbf299415,0xbf3fc767,0xbf3ca003,0xbf2d1469,
0xbef15aea,0xbf61c598,0xbf14b039,0xbf5064af,0xbf2e3bde,0xbf3b8f3b,0xbf44e3f5,0xbf239da9,0xbf584853,0xbf08f59b,0xbf6816a8,0xbed8106b,0xbf740bdd,0xbe9aa086,0xbf7bf531,0xbe354098,
0xbe47c5c2,0xbf7b14be,0xbe9aa086,0xbf740bdd,0xbecf7bca,0xbf6a09a7,0xbf00e7e4,0xbf5d2d53,0xbf187fc0,0xbf4d9f02,0xbf2e3bde,0xbf3b8f3b,0xbf41d870,0xbf273656,0xbf531849,0xbf10d3cd,
0xbf0e39da,0xbf54db31,0xbf299415,0xbf3fc767,0xbf41d870,0xbf273656,0xbf5695e5,0xbf0b9a6b,0xbf676bd8,0xbedae880,0xbf740bdd,0xbe9aa086,0xbf7c3b28,0xbe2f10a2,0xbf7fd397,0xbd16c32c,
0xbe94a031,0xbf74fa0b,0xbecc9b8b,0xbf6aab7b,0xbf00e7e4,0xbf5d2d53,0xbf19c200,0xbf4cae79,0xbf3085bb,0xbf396842,0xbf44e3f5,0xbf239da9,0xbf5695e5,0xbf0b9a6b,0xbf655e0b,0xbee363fa,
0xbf226799,0xbf45e403,0xbf3ca003,0xbf2d1469,0xbf531849,0xbf10d3cd,0xbf655e0b,0xbee363fa,0xbf731447,0xbea09ae5,0xbf7bf531,0xbe354098,0xbf7fd397,0xbd16c32c,0xbf7e9bc9,0x3dd53db9,
0xbf3504f3,0xbf3504f3,0xbf4d9f02,0xbf187fc0,0xbf61c598,0xbef15aea,0xbf710908,0xbeac7cd4,0xbf7b14be,0xbe47c5c2,0xbf7fb10f,0xbd48fb30,0xbf7ec46d,0x3dc8bd36,0xbf7853f8,0x3e78cfcc,
0xbf6c835e,0xbec3ef15,0xbf79c79d,0xbe605c13,0xbf7fb10f,0xbd48fb30,0xbf7e1324,0x3dfab273,0xbf74fa0b,0x3e94a031,0xbf64aa59,0x3ee63375,0xbf4d9f02,0x3f187fc0,0xbf3085bb,0x3f396842,
0xbf45e403,0xbf226799,0xbf5c61c7,0xbf0242b1,0xbf6db293,0xbebe1d4a,0xbf796e4e,0xbe667c66,0xbf7f4e6d,0xbd96a905,0xbf7f2f9d,0x3da3308c,0xbf791298,0x3e6c9a7f,0xbf6d1c1d,0x3ec1071e,
0xbf74fa0b,0xbe94a031,0xbf7e4323,0xbdee3876,0xbf7f84ab,0x3d7b2b74,0xbf78b47b,0x3e72b651,0xbf6a09a7,0x3ecf7bca,0xbf53fac3,0x3f0f8784,0xbf373a23,0x3f32c8c9,0xbf14b039,0x3f5064af,
0xbf54db31,0xbf0e39da,0xbf68bf3c,0xbed53641,0xbf76ba07,0xbe888e93,0xbf7e70b0,0xbde1bc2e,0xbf7fb10f,0x3d48fb30,0xbf7a7302,0x3e541501,0xbf6ed89e,0x3eb8442a,0xbf5d2d53,0x3f00e7e4,
0xbf7b14be,0xbe47c5c2,0xbf7ffb11,0xbc490e90,0xbf7c3b28,0x3e2f10a2,0xbf6ff573,0x3eb263ef,0xbf5b941a,0x3f039c3d,0xbf3fc767,0x3f299415,0xbf1d7fd1,0x3f49d112,0xbeebcbbb,0x3f633c5a,
0xbf61c598,0xbef15aea,0xbf7294f8,0xbea395c5,0xbf7cbfc9,0xbe22abb6,0xbf7ffec4,0x3bc90f88,0xbf7c3b28,0x3e2f10a2,0xbf718f57,0x3ea986c4,0xbf604621,0x3ef6e0cb,0xbf48d8b3,0x3f1ebc12,
0xbf7ec46d,0xbdc8bd36,0xbf7eea9d,0x3dbc3ac3,0xbf75dec6,0x3e8e9a22,0xbf63f473,0x3ee900b7,0xbf49d112,0x3f1d7fd1,0xbf286605,0x3f40d0da,0xbf00e7e4,0x3f5d2d53,0xbea986c4,0x3f718f57,
0x3f800000,0x0,0x3f800000,0x0,0x3f800000,0x0,0x3f800000,0x0,0x3f800000,0x0,0x3f800000,0x0,0x3f800000,0x0,0x3f800000,0x0,
0x3f54db31,0xbf0e39da,0x3f514d3d,0xbf13682a,0x3f4d9f02,0xbf187fc0,0x3f49d112,0xbf1d7fd1,0x3f45e403,0xbf226799,0x3f41d870,0xbf273656,0x3f3daef9,0xbf2beb4a,0x3f396842,0xbf3085bb,
0x3f7d3aac,0xbe164083,0x3f7cfe73,0xbe1c76de,0x3f7cbfc9,0xbe22abb6,0x3f7c7eb0,0xbe28defc,0x3f7c3b28,0xbe2f10a2,0x3f7bf531,0xbe354098,0x3f7baccd,0xbe3b6ecf,0x3f7b61fc,0xbe419b37,
0x3f3daef9,0xbf2beb4a,0x3f385216,0xbf31a81d,0x3f32c8c9,0xbf373a23,0x3f2d1469,0xbf3ca003,0x3f273656,0xbf41d870,0x3f212ff9,0xbf46e22a,0x3f1b02c6,0xbf4bbbf8,0x3f14b039,0xbf5064af,
0x3f74fa0b,0xbe94a031,0x3f740bdd,0xbe9aa086,0x3f731447,0xbea09ae5,0x3f721352,0xbea68f12,0x3f710908,0xbeac7cd4,0x3f6ff573,0xbeb263ef,0x3f6ed89e,0xbeb8442a,0x3f6db293,0xbebe1d4a,
0x3f226799,0xbf45e403,0x3f1b02c6,0xbf4bbbf8,0x3f13682a,0xbf514d3d,0x3f0b9a6b,0xbf5695e5,0x3f039c3d,0xbf5b941a,0x3ef6e0cb,0xbf604621,0x3ee63375,0xbf64aa59,0x3ed53641,0xbf68bf3c,
0x3f676bd8,0xbedae880,0x3f655e0b,0xbee363fa,0x3f633c5a,0xbeebcbbb,0x3f6106f2,0xbef41f07,0x3f5ebe05,0xbefc5d27,0x3f5c61c7,0xbf0242b1,0x3f59f26a,0xbf064b82,0x3f577026,0xbf0a48ad,
0x3f039c3d,0xbf5b941a,0x3ef41f07,0xbf6106f2,0x3ee0924f,0xbf660f88,0x3ecc9b8b,0xbf6aab7b,0x3eb8442a,0xbf6ed89e,0x3ea395c5,0xbf7294f8,0x3e8e9a22,0xbf75dec6,0x3e72b651,0xbf78b47b,
0x3ec3ef15,0xbf6c835e,0x3eac7cd4,0xbf710908,0x3e94a031,0xbf74fa0b,0x3e78cfcc,0xbf7853f8,0x3e47c5c2,0xbf7b14be,0x3e164083,0xbf7d3aac,0x3dc8bd36,0xbf7ec46d,0x3d48fb30,0xbf7fb10f,
0xbe47c5c2,0xbf7b14be,0xbe888e93,0xbf76ba07,0xbeac7cd4,0xbf710908,0xbecf7bca,0xbf6a09a7,0xbef15aea,0xbf61c598,0xbf08f59b,0xbf584853,0xbf187fc0,0xbf4d9f02,0xbf273656,0xbf41d870,
0x3e78cfcc,0xbf7853f8,0x3e419b37,0xbf7b61fc,0x3e09cf86,0xbf7dabcc,0x3da3308c,0xbf7f2f9d,0x3cc90ab0,0xbf7fec43,0xbcfb49ba,0xbf7fe129,0xbdafb680,0xbf7f0e58,0xbe1008b7,0xbf7d7474,
0xbeac7cd4,0xbf710908,0xbed25a09,0xbf696591,0xbef6e0cb,0xbf604621,0xbf0cead0,0xbf55b993,0xbf1d7fd1,0xbf49d112,0xbf2d1469,0xbf3ca003,0xbf3b8f3b,0xbf2e3bde,0xbf48d8b3,0xbf1ebc12,
0x3dc8bd36,0xbf7ec46d,0x3d16c32c,0xbf7fd397,0xbcc90ab0,0xbf7fec43,0xbdafb680,0xbf7f0e58,0xbe164083,0xbf7d3aac,0xbe541501,0xbf7a7302,0xbe888e93,0xbf76ba07,0xbea68f12,0xbf721352,
0xbef15aea,0xbf61c598,0xbf0b9a6b,0xbf5695e5,0xbf1d7fd1,0xbf49d112,0xbf2e3bde,0xbf3b8f3b,0xbf3daef9,0xbf2beb4a,0xbf4bbbf8,0xbf1b02c6,0xbf584853,0xbf08f59b,0xbf633c5a,0xbeebcbbb,
0xbd48fb30,0xbf7fb10f,0xbdee3876,0xbf7e4323,0xbe3b6ecf,0xbf7baccd,0xbe7ee6e1,0xbf77f110,0xbea09ae5,0xbf731447,0xbec1071e,0xbf6d1c1d,0xbee0924f,0xbf660f88,0xbeff17b2,0xbf5df6be,
0xbf187fc0,0xbf4d9f02,0xbf2ac082,0xbf3ebc1b,0xbf3b8f3b,0xbf2e3bde,0xbf4ac77f,0xbf1c420c,0xbf584853,0xbf08f59b,0xbf63f473,0xbee900b7,0xbf6db293,0xbebe1d4a,0xbf756d97,0xbe919ddd,
0xbf3504f3,0xbf3504f3,0xbf45e403,0xbf226799,0xbf54db31,0xbf0e39da,0xbf61c598,0xbef15aea,0xbf6c835e,0xbec3ef15,0xbf74fa0b,0xbe94a031,0xbf7b14be,0xbe47c5c2,0xbf7ec46d,0xbdc8bd36,
0xbf7b14be,0xbe47c5c2,0xbf7f4e6d,0xbd96a905,0xbf7fb10f,0x3d48fb30,0xbf7c3b28,0x3e2f10a2,0xbf74fa0b,0x3e94a031,0xbf6a09a7,0x3ecf7bca,0xbf5b941a,0x3f039c3d,0xbf49d112,0x3f1d7fd1,
0xbf4d9f02,0xbf187fc0,0xbf5c61c7,0xbf0242b1,0xbf68bf3c,0xbed53641,0xbf7294f8,0xbea395c5,0xbf79c79d,0xbe605c13,0xbf7e4323,0xbdee3876,0xbf7ffb11,0xbc490e90,0xbf7eea9d,0x3dbc3ac3,
0xbf7fb10f,0xbd48fb30,0xbf7f2f9d,0x3da3308c,0xbf7a7302,0x3e541501,0xbf718f57,0x3ea986c4,0xbf64aa59,0x3ee63375,0xbf53fac3,0x3f0f8784,0xbf3fc767,0x3f299415,0xbf286605,0x3f40d0da,
0xbf61c598,0xbef15aea,0xbf6db293,0xbebe1d4a,0xbf76ba07,0xbe888e93,0xbf7cbfc9,0xbe22abb6,0xbf7fb10f,0xbd48fb30,0xbf7f84ab,0x3d7b2b74,0xbf7c3b28,0x3e2f10a2,0xbf75dec6,0x3e8e9a22,
0xbf7ec46d,0x3dc8bd36,0xbf791298,0x3e6c9a7f,0xbf6ed89e,0x3eb8442a,0xbf604621,0x3ef6e0cb,0xbf4d9f02,0x3f187fc0,0xbf373a23,0x3f32c8c9,0xbf1d7fd1,0x3f49d112,0xbf00e7e4,0x3f5d2d53,
0xbf710908,0xbeac7cd4,0xbf796e4e,0xbe667c66,0xbf7e70b0,0xbde1bc2e,0xbf7ffec4,0x3bc90f88,0xbf7e1324,0x3dfab273,0xbf78b47b,0x3e72b651,0xbf6ff573,0x3eb263ef,0xbf63f473,0x3ee900b7,
0xbf7853f8,0x3e78cfcc,0xbf6d1c1d,0x3ec1071e,0xbf5d2d53,0x3f00e7e4,0xbf48d8b3,0x3f1ebc12,0xbf3085bb,0x3f396842,0xbf14b039,0x3f5064af,0xbeebcbbb,0x3f633c5a,0xbea986c4,0x3f718f57,
0xbf6c835e,0x3ec3ef15,0xbf5b941a,0x3f039c3d,0xbf45e403,0x3f226799,0xbf2beb4a,0x3f3daef9,0xbf0e39da,0x3f54db31,0xbedae880,0x3f676bd8,0xbe94a031,0x3f74fa0b,0xbe164083,0x3f7d3aac,
0xbf0e39da,0x3f54db31,0xbecf7bca,0x3f6a09a7,0xbe78cfcc,0x3f7853f8,0xbd96a905,0x3f7f4e6d,0x3dc8bd36,0x3f7ec46d,0x3e888e93,0x3f76ba07,0x3edae880,0x3f676bd8,0x3f13682a,0x3f514d3d,
0xbf5b941a,0x3f039c3d,0xbf44e3f5,0x3f239da9,0xbf299415,0x3f3fc767,0xbf0a48ad,0x3f577026,0xbecf7bca,0x3f6a09a7,0xbe8586ce,0x3f772417,0xbde1bc2e,0x3f7e70b0,0x3d2fe007,0x3f7fc38f,
0xbedae880,0x3f676bd8,0xbe8586ce,0x3f772417,0xbdafb680,0x3f7f0e58,0x3dbc3ac3,0x3f7eea9d,0x3e888e93,0x3f76ba07,0x3eddbe79,0x3f66becc,0x3f15f6d9,0x3f4f7a1f,0x3f385216,0x3f31a81d,
0xbf45e403,0x3f226799,0xbf299415,0x3f3fc767,0xbf08f59b,0x3f584853,0xbec9b953,0x3f6b4b0c,0xbe78cfcc,0x3f7853f8,0xbdafb680,0x3f7f0e58,0x3d96a905,0x3f7f4e6d,0x3e6c9a7f,0x3f791298,
0xbe94a031,0x3f74fa0b,0xbde1bc2e,0x3f7e70b0,0x3d96a905,0x3f7f4e6d,0x3e827dc0,0x3f778bc5,0x3edae880,0x3f676bd8,0x3f15f6d9,0x3f4f7a1f,0x3f396842,0x3f3085bb,0x3f5695e5,0x3f0b9a6b,
0xbf2beb4a,0x3f3daef9,0xbf0a48ad,0x3f577026,0xbec9b953,0x3f6b4b0c,0xbe72b651,0x3f78b47b,0xbd96a905,0x3f7f4e6d,0x3dbc3ac3,0x3f7eea9d,0x3e827dc0,0x3f778bc5,0x3ed25a09,0x3f696591,
0xbe164083,0x3f7d3aac,0x3d2fe007,0x3f7fc38f,0x3e6c9a7f,0x3f791298,0x3ed25a09,0x3f696591,0x3f13682a,0x3f514d3d,0x3f385216,0x3f31a81d,0x3f5695e5,0x3f0b9a6b,0x3f6d1c1d,0x3ec1071e,
0x3e00,0x3e00,0x3e00,0x3e00,0x3e00,0x3e00,0x3e00,0x3e00,0x3e00,0x3e00,0x3e00,0x3e00,0x3e00,0x3e00,0x3e00,0x3e00,
0xbd443ded,0xbcc83dfb,0xbc493dff,0xbd153df5,0xbdb53db5,0xbdd53d8e,0xbdc63da2,0xbde23d71,0xbe000000,0xbdfbbcc8,0xbdffbc49,0xbdf5bd15,0xbdb5bdb5,0xbd8ebdd5,0xbda2bdc6,0xbd71bde2,
0xbdb53db5,0xbd443ded,0xbcc83dfb,0xbd8e3dd5,0xbe000000,0xbdedbd44,0xbdfbbcc8,0xbdd5bd8e,0xbe00,0x3d44bded,0x3cc8bdfb,0x3d8ebdd5,0x3e000000,0x3ded3d44,0x3dfb3cc8,0x3dd53d8e,
0xbded3d44,0xbd8e3dd5,0xbd153df5,0xbdc63da2,0xbdb5bdb5,0xbcc8bdfb,0xbd71bde2,0x3c49bdff,0x3e000000,0x3dd53d8e,0x3df53d15,0x3da23dc6,0xbdb53db5,0xbdfb3cc8,0xbde23d71,0xbdffbc49,
0xbe000000,0xbdb53db5,0xbd443ded,0xbded3d44,0xbe00,0x3db5bdb5,0x3d44bded,0x3dedbd44,0x3e00,0xbdb53db5,0xbd443ded,0xbded3d44,0xbe00,0x3db5bdb5,0x3d44bded,0x3dedbd44,
0xbdedbd44,0xbdd53d8e,0xbd713de2,0xbdff3c49,0x3db5bdb5,0x3dfb3cc8,0x3df5bd15,0x3dc63da2,0xbe000000,0xbd8ebdd5,0xbde2bd71,0xbc49bdff,0x3db53db5,0xbcc83dfb,0x3d153df5,0xbda23dc6,
0xbdb5bdb5,0xbded3d44,0xbd8e3dd5,0xbdfbbcc8,0x3e000000,0x3d443ded,0x3dd53d8e,0xbcc83dfb,0xbe00,0x3dedbd44,0x3d8ebdd5,0x3dfb3cc8,0xbe000000,0xbd44bded,0xbdd5bd8e,0x3cc8bdfb,
0xbd44bded,0xbdfb3cc8,0xbda23dc6,0xbde2bd71,0x3db53db5,0xbd8e3dd5,0x3c493dff,0xbdf53d15,0x3e000000,0x3cc83dfb,0x3dc63da2,0xbd713de2,0x3db5bdb5,0x3dd53d8e,0x3dffbc49,0x3d153df5,
0xbe00,0xbe000000,0xbdb53db5,0xbdb5bdb5,0x3e00,0xbe000000,0xbdb53db5,0xbdb5bdb5,0x3e00,0xbe000000,0xbdb53db5,0xbdb5bdb5,0x3e00,0xbe000000,0xbdb53db5,0xbdb5bdb5,
0x3d44bded,0xbdfbbcc8,0xbdc63da2,0xbd71bde2,0xbdb53db5,0xbd8ebdd5,0xbdffbc49,0x3d15bdf5,0xbe000000,0x3cc8bdfb,0xbda2bdc6,0x3de2bd71,0xbdb5bdb5,0x3dd5bd8e,0x3c49bdff,0x3df53d15,
0x3db5bdb5,0xbdedbd44,0xbdd53d8e,0xbcc8bdfb,0xbe000000,0x3d44bded,0xbd8ebdd5,0x3dfbbcc8,0xbe00,0x3ded3d44,0x3dd5bd8e,0x3cc83dfb,0x3e000000,0xbd443ded,0x3d8e3dd5,0xbdfb3cc8,
0x3dedbd44,0xbdd5bd8e,0xbde23d71,0x3c49bdff,0xbdb5bdb5,0x3dfbbcc8,0x3d15bdf5,0x3da23dc6,0x3e000000,0xbd8e3dd5,0x3d713de2,0xbdffbc49,0xbdb53db5,0xbcc8bdfb,0xbdf5bd15,0x3dc6bda2,
0x3e000000,0xbdb5bdb5,0xbded3d44,0x3d44bded,0xbe00,0x3db53db5,0x3dedbd44,0xbd443ded,0x3e00,0xbdb5bdb5,0xbded3d44,0x3d44bded,0xbe00,0x3db53db5,0x3dedbd44,0xbd443ded,
0x3ded3d44,0xbd8ebdd5,0xbdf53d15,0x3da2bdc6,0x3db5bdb5,0xbcc83dfb,0x3de23d71,0xbdff3c49,0xbe000000,0x3dd5bd8e,0xbd15bdf5,0x3dc63da2,0x3db53db5,0xbdfbbcc8,0xbd713de2,0xbc49bdff,
0x3db53db5,0xbd44bded,0xbdfb3cc8,0x3dd5bd8e,0x3e000000,0xbded3d44,0x3cc83dfb,0xbd8ebdd5,0xbe00,0x3d443ded,0x3dfbbcc8,0xbdd53d8e,0xbe000000,0x3dedbd44,0xbcc8bdfb,0x3d8e3dd5,
0x3d443ded,0xbcc8bdfb,0xbdff3c49,0x3df5bd15,0x3db53db5,0xbdd5bd8e,0xbda23dc6,0x3d71bde2,0x3e000000,0xbdfb3cc8,0x3c493dff,0xbd15bdf5,0x3db5bdb5,0xbd8e3dd5,0x3dc63da2,0xbde2bd71,
0x3e00,0xbe00,0xbe000000,0x3e000000,0x3e00,0xbe00,0xbe000000,0x3e000000,0x3e00,0xbe00,0xbe000000,0x3e000000,0x3e00,0xbe00,0xbe000000,0x3e000000,
0xbd443ded,0x3cc8bdfb,0xbdffbc49,0x3df53d15,0xbdb53db5,0x3dd5bd8e,0xbda2bdc6,0x3d713de2,0xbe000000,0x3dfb3cc8,0x3c49bdff,0xbd153df5,0xbdb5bdb5,0x3d8e3dd5,0x3dc6bda2,0xbde23d71,
0xbdb53db5,0x3d44bded,0xbdfbbcc8,0x3dd53d8e,0xbe000000,0x3ded3d44,0x3cc8bdfb,0xbd8e3dd5,0xbe00,0xbd443ded,0x3dfb3cc8,0xbdd5bd8e,0x3e000000,0xbdedbd44,0xbcc83dfb,0x3d8ebdd5,
0xbded3d44,0x3d8ebdd5,0xbdf5bd15,0x3da23dc6,0xbdb5bdb5,0x3cc83dfb,0x3de2bd71,0xbdffbc49,0x3e000000,0xbdd5bd8e,0xbd153df5,0x3dc6bda2,0xbdb53db5,0x3dfbbcc8,0xbd71bde2,0xbc493dff,
0xbe000000,0x3db5bdb5,0xbdedbd44,0x3d443ded,0xbe00,0xbdb53db5,0x3ded3d44,0xbd44bded,0x3e00,0x3db5bdb5,0xbdedbd44,0x3d443ded,0xbe00,0xbdb53db5,0x3ded3d44,0xbd44bded,
0xbdedbd44,0x3dd5bd8e,0xbde2bd71,0x3c493dff,0x3db5bdb5,0xbdfbbcc8,0x3d153df5,0x3da2bdc6,0xbe000000,0x3d8e3dd5,0x3d71bde2,0xbdff3c49,0x3db53db5,0x3cc8bdfb,0xbdf53d15,0x3dc63da2,
0xbdb5bdb5,0x3dedbd44,0xbdd5bd8e,0xbcc83dfb,0x3e000000,0xbd44bded,0xbd8e3dd5,0x3dfb3cc8,0xbe00,0xbded3d44,0x3dd53d8e,0x3cc8bdfb,0xbe000000,0x3d443ded,0x3d8ebdd5,0xbdfbbcc8,
0xbd44bded,0x3dfbbcc8,0xbdc6bda2,0xbd713de2,0x3db53db5,0x3d8ebdd5,0xbdff3c49,0x3d153df5,0x3e000000,0xbcc8bdfb,0xbda23dc6,0x3de23d71,0x3db5bdb5,0xbdd5bd8e,0x3c493dff,0x3df5bd15,
0xbe00,0x3e000000,0xbdb5bdb5,0xbdb53db5,0x3e00,0x3e000000,0xbdb5bdb5,0xbdb53db5,0x3e00,0x3e000000,0xbdb5bdb5,0xbdb53db5,0x3e00,0x3e000000,0xbdb5bdb5,0xbdb53db5,
0x3d44bded,0x3dfb3cc8,0xbda2bdc6,0xbde23d71,0xbdb53db5,0x3d8e3dd5,0x3c49bdff,0xbdf5bd15,0xbe000000,0xbcc83dfb,0x3dc6bda2,0xbd71bde2,0xbdb5bdb5,0xbdd53d8e,0x3dff3c49,0x3d15bdf5,
0x3db5bdb5,0x3ded3d44,0xbd8ebdd5,0xbdfb3cc8,0xbe000000,0xbd443ded,0x3dd5bd8e,0xbcc8bdfb,0xbe00,0xbdedbd44,0x3d8e3dd5,0x3dfbbcc8,0x3e000000,0x3d44bded,0xbdd53d8e,0x3cc83dfb,
0x3dedbd44,0x3dd53d8e,0xbd71bde2,0xbdffbc49,0xbdb5bdb5,0xbdfb3cc8,0x3df53d15,0x3dc6bda2,0x3e000000,0x3d8ebdd5,0xbde23d71,0xbc493dff,0xbdb53db5,0x3cc83dfb,0x3d15bdf5,0xbda2bdc6,
0x3e000000,0x3db53db5,0xbd44bded,0xbdedbd44,0xbe00,0xbdb5bdb5,0x3d443ded,0x3ded3d44,0x3e00,0x3db53db5,0xbd44bded,0xbdedbd44,0xbe00,0xbdb5bdb5,0x3d443ded,0x3ded3d44,
0x3ded3d44,0x3d8e3dd5,0xbd15bdf5,0xbdc6bda2,0x3db5bdb5,0x3cc8bdfb,0xbd713de2,0x3c493dff,0xbe000000,0xbdd53d8e,0x3df5bd15,0x3da2bdc6,0x3db53db5,0x3dfb3cc8,0xbde2bd71,0xbdff3c49,
0x3db53db5,0x3d443ded,0xbcc8bdfb,0xbd8ebdd5,0x3e000000,0x3dedbd44,0xbdfb3cc8,0xbdd53d8e,0xbe00,0xbd44bded,0x3cc83dfb,0x3d8e3dd5,0xbe000000,0xbded3d44,0x3dfbbcc8,0x3dd5bd8e,
0x3d443ded,0x3cc83dfb,0xbc49bdff,0xbd15bdf5,0x3db53db5,0x3dd53d8e,0xbdc6bda2,0xbde2bd71,0x3e000000,0x3dfbbcc8,0xbdff3c49,0xbdf53d15,0x3db5bdb5,0x3d8ebdd5,0xbda23dc6,0xbd713de2,
0x3d803d80,0x3e00,0x3e00,0x3e00,0x3e00,0x3e00,0x3e00,0x3e00,0x3e00,0x3e00,0x3e00,0x3e00,0x3e00,0x3e00,0x3e00,0x3e00,
0xbd803d80,0x3cc8bdfb,0x3c49bdff,0x3d15bdf5,0xbded3d44,0x3dd5bd8e,0x3dc6bda2,0x3de2bd71,0xbdedbd44,0x3dfb3cc8,0x3dff3c49,0x3df53d15,0xbd44bded,0x3d8e3dd5,0x3da23dc6,0x3d713de2,
0x3d803d80,0xbd443ded,0xbcc83dfb,0xbd8e3dd5,0xbdb5bdb5,0xbdedbd44,0xbdfbbcc8,0xbdd5bd8e,0x3db5bdb5,0x3d44bded,0x3cc8bdfb,0x3d8ebdd5,0x3db53db5,0x3ded3d44,0x3dfb3cc8,0x3dd53d8e,
0xbd803d80,0x3d8ebdd5,0x3d15bdf5,0x3dc6bda2,0x3d44bded,0x3cc83dfb,0x3d713de2,0xbc493dff,0x3d443ded,0xbdd5bd8e,0xbdf5bd15,0xbda2bdc6,0xbdedbd44,0x3dfbbcc8,0x3de2bd71,0x3dff3c49,
0x3d803d80,0xbdb53db5,0xbd443ded,0xbded3d44,0x3e000000,0x3db5bdb5,0x3d44bded,0x3dedbd44,0xbe000000,0xbdb53db5,0xbd443ded,0xbded3d44,0x3e000000,0x3db5bdb5,0x3d44bded,0x3dedbd44,
0xbd803d80,0x3dd5bd8e,0x3d71bde2,0x3dffbc49,0x3d443ded,0xbdfbbcc8,0xbdf53d15,0xbdc6bda2,0x3d44bded,0x3d8e3dd5,0x3de23d71,0x3c493dff,0xbded3d44,0x3cc8bdfb,0xbd15bdf5,0x3da2bdc6,
0x3d803d80,0xbded3d44,0xbd8e3dd5,0xbdfbbcc8,0xbdb53db5,0x3d443ded,0x3dd53d8e,0xbcc83dfb,0x3db53db5,0x3dedbd44,0x3d8ebdd5,0x3dfb3cc8,0x3db5bdb5,0xbd44bded,0xbdd5bd8e,0x3cc8bdfb,
0xbd803d80,0x3dfbbcc8,0x3da2bdc6,0x3de23d71,0xbdedbd44,0x3d8ebdd5,0xbc49bdff,0x3df5bd15,0xbded3d44,0xbcc8bdfb,0xbdc6bda2,0x3d71bde2,0xbd443ded,0xbdd5bd8e,0xbdff3c49,0xbd15bdf5,
0x3d803d80,0xbe000000,0xbdb53db5,0xbdb5bdb5,0xbe00,0xbe000000,0xbdb53db5,0xbdb5bdb5,0xbe00,0xbe000000,0xbdb53db5,0xbdb5bdb5,0xbe00,0xbe000000,0xbdb53db5,0xbdb5bdb5,
0xbd803d80,0x3dfb3cc8,0x3dc6bda2,0x3d713de2,0x3dedbd44,0x3d8e3dd5,0x3dff3c49,0xbd153df5,0x3ded3d44,0xbcc83dfb,0x3da23dc6,0xbde23d71,0x3d443ded,0xbdd53d8e,0xbc493dff,0xbdf5bd15,
0x3d803d80,0xbdedbd44,0xbdd53d8e,0xbcc8bdfb,0x3db53db5,0x3d44bded,0xbd8ebdd5,0x3dfbbcc8,0xbdb53db5,0x3ded3d44,0x3dd5bd8e,0x3cc83dfb,0xbdb5bdb5,0xbd443ded,0x3d8e3dd5,0xbdfb3cc8,
0xbd803d80,0x3dd53d8e,0x3de2bd71,0xbc493dff,0xbd443ded,0xbdfb3cc8,0xbd153df5,0xbda2bdc6,0xbd44bded,0x3d8ebdd5,0xbd71bde2,0x3dff3c49,0x3ded3d44,0x3cc83dfb,0x3df53d15,0xbdc63da2,
0x3d803d80,0xbdb5bdb5,0xbded3d44,0x3d44bded,0xbe000000,0x3db53db5,0x3dedbd44,0xbd443ded,0x3e000000,0xbdb5bdb5,0xbded3d44,0x3d44bded,0xbe000000,0x3db53db5,0x3dedbd44,0xbd443ded,
0xbd803d80,0x3d8e3dd5,0x3df5bd15,0xbda23dc6,0xbd44bded,0x3cc8bdfb,0xbde2bd71,0x3dffbc49,0xbd443ded,0xbdd53d8e,0x3d153df5,0xbdc6bda2,0x3dedbd44,0x3dfb3cc8,0x3d71bde2,0x3c493dff,
0x3d803d80,0xbd44bded,0xbdfb3cc8,0x3dd5bd8e,0x3db5bdb5,0xbded3d44,0x3cc83dfb,0xbd8ebdd5,0xbdb5bdb5,0x3d443ded,0x3dfbbcc8,0xbdd53d8e,0xbdb53db5,0x3dedbd44,0xbcc8bdfb,0x3d8e3dd5,
0xbd803d80,0x3cc83dfb,0x3dffbc49,0xbdf53d15,0x3ded3d44,0x3dd53d8e,0x3da2bdc6,0xbd713de2,0x3dedbd44,0x3dfbbcc8,0xbc49bdff,0x3d153df5,0x3d44bded,0x3d8ebdd5,0xbdc6bda2,0x3de23d71,
0x3d803d80,0xbe00,0xbe000000,0x3e000000,0x3e00,0xbe00,0xbe000000,0x3e000000,0x3e00,0xbe00,0xbe000000,0x3e000000,0x3e00,0xbe00,0xbe000000,0x3e000000,
0xbd803d80,0xbcc83dfb,0x3dff3c49,0xbdf5bd15,0xbded3d44,0xbdd53d8e,0x3da23dc6,0xbd71bde2,0xbdedbd44,0xbdfbbcc8,0xbc493dff,0x3d15bdf5,0xbd44bded,0xbd8ebdd5,0xbdc63da2,0x3de2bd71,
0x3d803d80,0x3d44bded,0xbdfbbcc8,0x3dd53d8e,0xbdb5bdb5,0x3ded3d44,0x3cc8bdfb,0xbd8e3dd5,0x3db5bdb5,0xbd443ded,0x3dfb3cc8,0xbdd5bd8e,0x3db53db5,0xbdedbd44,0xbcc83dfb,0x3d8ebdd5,
0xbd803d80,0xbd8e3dd5,0x3df53d15,0xbda2bdc6,0x3d44bded,0xbcc8bdfb,0xbde23d71,0x3dff3c49,0x3d443ded,0x3dd53d8e,0x3d15bdf5,0xbdc63da2,0xbdedbd44,0xbdfb3cc8,0x3d713de2,0x3c49bdff,
0x3d803d80,0x3db5bdb5,0xbdedbd44,0x3d443ded,0x3e000000,0xbdb53db5,0x3ded3d44,0xbd44bded,0xbe000000,0x3db5bdb5,0xbdedbd44,0x3d443ded,0x3e000000,0xbdb53db5,0x3ded3d44,0xbd44bded,
0xbd803d80,0xbdd53d8e,0x3de23d71,0xbc49bdff,0x3d443ded,0x3dfb3cc8,0xbd15bdf5,0xbda23dc6,0x3d44bded,0xbd8ebdd5,0xbd713de2,0x3dffbc49,0xbded3d44,0xbcc83dfb,0x3df5bd15,0xbdc6bda2,
0x3d803d80,0x3dedbd44,0xbdd5bd8e,0xbcc83dfb,0xbdb53db5,0xbd44bded,0xbd8e3dd5,0x3dfb3cc8,0x3db53db5,0xbded3d44,0x3dd53d8e,0x3cc8bdfb,0x3db5bdb5,0x3d443ded,0x3d8ebdd5,0xbdfbbcc8,
0xbd803d80,0xbdfb3cc8,0x3dc63da2,0x3d71bde2,0xbdedbd44,0xbd8e3dd5,0x3dffbc49,0xbd15bdf5,0xbded3d44,0x3cc83dfb,0x3da2bdc6,0xbde2bd71,0xbd443ded,0x3dd53d8e,0xbc49bdff,0xbdf53d15,
0x3d803d80,0x3e000000,0xbdb5bdb5,0xbdb53db5,0xbe00,0x3e000000,0xbdb5bdb5,0xbdb53db5,0xbe00,0x3e000000,0xbdb5bdb5,0xbdb53db5,0xbe00,0x3e000000,0xbdb5bdb5,0xbdb53db5,
0xbd803d80,0xbdfbbcc8,0x3da23dc6,0x3de2bd71,0x3dedbd44,0xbd8ebdd5,0xbc493dff,0x3df53d15,0x3ded3d44,0x3cc8bdfb,0xbdc63da2,0x3d713de2,0x3d443ded,0x3dd5bd8e,0xbdffbc49,0xbd153df5,
0x3d803d80,0x3ded3d44,0xbd8ebdd5,0xbdfb3cc8,0x3db53db5,0xbd443ded,0x3dd5bd8e,0xbcc8bdfb,0xbdb53db5,0xbdedbd44,0x3d8e3dd5,0x3dfbbcc8,0xbdb5bdb5,0x3d44bded,0xbdd53d8e,0x3cc83dfb,
0xbd803d80,0xbdd5bd8e,0x3d713de2,0x3dff3c49,0xbd443ded,0x3dfbbcc8,0xbdf5bd15,0xbdc63da2,0xbd44bded,0xbd8e3dd5,0x3de2bd71,0x3c49bdff,0x3ded3d44,0xbcc8bdfb,0xbd153df5,0x3da23dc6,
0x3d803d80,0x3db53db5,0xbd44bded,0xbdedbd44,0xbe000000,0xbdb5bdb5,0x3d443ded,0x3ded3d44,0x3e000000,0x3db53db5,0xbd44bded,0xbdedbd44,0xbe000000,0xbdb5bdb5,0x3d443ded,0x3ded3d44,
0xbd803d80,0xbd8ebdd5,0x3d153df5,0x3dc63da2,0xbd44bded,0xbcc83dfb,0x3d71bde2,0xbc49bdff,0xbd443ded,0x3dd5bd8e,0xbdf53d15,0xbda23dc6,0x3dedbd44,0xbdfbbcc8,0x3de23d71,0x3dffbc49,
0x3d803d80,0x3d443ded,0xbcc8bdfb,0xbd8ebdd5,0x3db5bdb5,0x3dedbd44,0xbdfb3cc8,0xbdd53d8e,0xbdb5bdb5,0xbd44bded,0x3cc83dfb,0x3d8e3dd5,0xbdb53db5,0xbded3d44,0x3dfbbcc8,0x3dd5bd8e,
0xbd803d80,0xbcc8bdfb,0x3c493dff,0x3d153df5,0x3ded3d44,0xbdd5bd8e,0x3dc63da2,0x3de23d71,0x3dedbd44,0xbdfb3cc8,0x3dffbc49,0x3df5bd15,0x3d44bded,0xbd8e3dd5,0x3da2bdc6,0x3d71bde2,
0xbc493dff,0xbbc93e00,0xbb493e00,0xbc173dff,0xbcc83dfb,0xbcf93df8,0xbce03dfa,0xbd093df7,0xbd443ded,0xbd5b3de7,0xbd4f3dea,0xbd663de5,0xbd8e3dd5,0xbd983dce,0xbd933dd1,0xbd9d3dca,
0xbd713de2,0xbcf93df8,0xbc7b3dfe,0xbd383def,0xbdd53d8e,0xbdf13d2c,0xbde53d66,0xbdfa3ce0,0xbdedbd44,0xbdcebd98,0xbddfbd7c,0xbdb9bdb1,0xbcc8bdfb,0x3bc9be00,0xbc17bdff,0x3cafbdfc,
0xbdc63da2,0xbd5b3de7,0xbce03dfa,0xbd9d3dca,0xbdfbbcc8,0xbdcebd98,0xbdeabd4f,0xbda7bdc2,0x3d44bded,0x3dbebdac,0x3d93bdd1,0x3ddfbd7c,0x3dd53d8e,0x3d843ddc,0x3db13db9,0x3d213df3,
0xbdf53d15,0xbd983dce,0xbd213df3,0xbdd13d93,0xbd8ebdd5,0x3bc9be00,0xbd09bdf7,0x3d38bdef,0x3ded3d44,0x3d843ddc,0x3dc23da7,0x3ce03dfa,0xbdfb3cc8,0xbde7bd5b,0xbdfebc7b,0xbdb9bdb1,
0xbdffbc49,0xbdbe3dac,0xbd4f3dea,0xbdf33d21,0x3cc8bdfb,0x3ddcbd84,0x3d93bdd1,0x3dfebc7b,0xbd443ded,0xbdf13d2c,0xbdb93db1,0xbdffbc17,0x3d8ebdd5,0x3dfdbc96,0x3dd8bd89,0x3df73d09,
0xbde2bd71,0xbddc3d84,0xbd7c3ddf,0xbe003b49,0x3dd5bd8e,0x3de73d5b,0x3dffbc17,0x3d933dd1,0xbdedbd44,0xbc96bdfd,0xbd9dbdca,0x3d38bdef,0x3cc83dfb,0xbdbe3dac,0xbd213df3,0xbdfa3ce0,
0xbda2bdc6,0xbdf13d2c,0xbd933dd1,0xbdf7bd09,0x3dfb3cc8,0x3c963dfd,0x3db13db9,0xbd663de5,0x3d44bded,0x3e003bc9,0x3dd8bd89,0x3dca3d9d,0xbdd5bd8e,0x3cf9bdf8,0xbd38bdef,0x3dc2bda7,
0xbd15bdf5,0xbdfd3c96,0xbda73dc2,0xbdd8bd89,0x3d8e3dd5,0xbdbe3dac,0xbc7b3dfe,0xbe003b49,0x3ded3d44,0xbcf93df8,0x3d663de5,0xbdd13d93,0x3dfbbcc8,0x3d2c3df1,0x3ddf3d7c,0xbd383def,
0x3c49bdff,0xbe00bbc9,0xbdb93db1,0xbda7bdc2,0xbcc83dfb,0xbdf8bcf9,0xbdd83d89,0xbd7cbddf,0xbd443ded,0xbde7bd5b,0xbdef3d38,0xbd21bdf3,0xbd8e3dd5,0xbdcebd98,0xbdfc3caf,0xbc7bbdfe,
0x3d71bde2,0xbdf8bcf9,0xbdca3d9d,0xbd4fbdea,0xbdd53d8e,0xbd2cbdf1,0xbdf3bd21,0x3d89bdd8,0xbdedbd44,0x3d98bdce,0xbd09bdf7,0x3e00bb49,0xbcc8bdfb,0x3e003bc9,0x3da7bdc2,0x3d933dd1,
0x3dc6bda2,0xbde7bd5b,0xbdd83d89,0xbc7bbdfe,0xbdfbbcc8,0x3d98bdce,0xbd38bdef,0x3dff3c17,0x3d44bded,0x3dac3dbe,0x3dfcbcaf,0xbd093df7,0x3dd53d8e,0xbddc3d84,0xbb493e00,0xbde5bd66,
0x3df5bd15,0xbdcebd98,0xbde53d66,0x3cafbdfc,0xbd8ebdd5,0x3e003bc9,0x3d7cbddf,0x3d4f3dea,0x3ded3d44,0xbddc3d84,0x3c173dff,0xbdd8bd89,0xbdfb3cc8,0x3d5bbde7,0xbd9dbdca,0x3e00bb49,
0x3dff3c49,0xbdacbdbe,0xbdef3d38,0x3d66bde5,0x3cc8bdfb,0x3d843ddc,0x3dfcbcaf,0xbd9d3dca,0xbd443ded,0xbd2cbdf1,0xbe00bb49,0x3dc2bda7,0x3d8ebdd5,0x3c963dfd,0x3dfa3ce0,0xbddf3d7c,
0x3de23d71,0xbd84bddc,0xbdf73d09,0x3db1bdb9,0x3dd5bd8e,0xbd5b3de7,0x3dc23da7,0xbdfcbcaf,0xbdedbd44,0x3dfdbc96,0x3c7bbdfe,0x3d4f3dea,0x3cc83dfb,0xbdacbdbe,0xbde53d66,0x3d89bdd8,
0x3da23dc6,0xbd2cbdf1,0xbdfc3caf,0x3ddfbd7c,0x3dfb3cc8,0xbdfd3c96,0xbb493e00,0xbd21bdf3,0x3d44bded,0xbbc93e00,0x3dfa3ce0,0xbdfe3c7b,0xbdd5bd8e,0x3df83cf9,0x3d4fbdea,0xbc173dff,
0x3d153df5,0xbc96bdfd,0xbdff3c17,0x3dfabce0,0x3d8e3dd5,0xbdacbdbe,0xbdca3d9d,0x3db1bdb9,0x3ded3d44,0xbdf8bcf9,0xbd213df3,0x3cafbdfc,0x3dfbbcc8,0xbdf13d2c,0x3d093df7,0xbd4fbdea,
0xbc493dff,0x3bc9be00,0xbe00bb49,0x3dff3c17,0xbcc83dfb,0x3cf9bdf8,0xbdfabce0,0x3df73d09,0xbd443ded,0x3d5bbde7,0xbdeabd4f,0x3de53d66,0xbd8e3dd5,0x3d98bdce,0xbdd1bd93,0x3dca3d9d,
0xbd713de2,0x3cf9bdf8,0xbdfebc7b,0x3def3d38,0xbdd53d8e,0x3df1bd2c,0xbd66bde5,0x3ce03dfa,0xbdedbd44,0x3dce3d98,0x3d7cbddf,0xbdb13db9,0xbcc8bdfb,0xbbc93e00,0x3dffbc17,0xbdfcbcaf,
0xbdc63da2,0x3d5bbde7,0xbdfabce0,0x3dca3d9d,0xbdfbbcc8,0x3dce3d98,0x3d4fbdea,0xbdc23da7,0x3d44bded,0xbdbe3dac,0x3dd13d93,0xbd7cbddf,0x3dd53d8e,0xbd84bddc,0xbdb93db1,0x3df3bd21,
0xbdf53d15,0x3d98bdce,0xbdf3bd21,0x3d933dd1,0xbd8ebdd5,0xbbc93e00,0x3df7bd09,0xbdefbd38,0x3ded3d44,0xbd84bddc,0xbda73dc2,0x3dfabce0,0xbdfb3cc8,0x3de73d5b,0x3c7bbdfe,0xbdb13db9,
0xbdffbc49,0x3dbebdac,0xbdeabd4f,0x3d213df3,0x3cc8bdfb,0xbddc3d84,0x3dd13d93,0xbc7bbdfe,0xbd443ded,0x3df1bd2c,0xbdb1bdb9,0xbc173dff,0x3d8ebdd5,0xbdfd3c96,0x3d893dd8,0x3d09bdf7,
0xbde2bd71,0x3ddcbd84,0xbddfbd7c,0x3b493e00,0x3dd5bd8e,0xbde7bd5b,0x3c173dff,0x3dd1bd93,0xbdedbd44,0x3c963dfd,0x3dcabd9d,0xbdefbd38,0x3cc83dfb,0x3dbebdac,0xbdf3bd21,0x3ce03dfa,
0xbda2bdc6,0x3df1bd2c,0xbdd1bd93,0xbd093df7,0x3dfb3cc8,0xbc96bdfd,0xbdb93db1,0x3de53d66,0x3d44bded,0xbe00bbc9,0x3d893dd8,0x3d9dbdca,0xbdd5bd8e,0xbcf93df8,0x3defbd38,0xbda7bdc2,
0xbd15bdf5,0x3dfdbc96,0xbdc2bda7,0xbd893dd8,0x3d8e3dd5,0x3dbebdac,0xbdfebc7b,0x3b493e00,0x3ded3d44,0x3cf9bdf8,0xbde53d66,0x3d933dd1,0x3dfbbcc8,0xbd2cbdf1,0xbd7c3ddf,0x3def3d38,
0x3c49bdff,0x3e003bc9,0xbdb1bdb9,0xbdc23da7,0xbcc83dfb,0x3df83cf9,0xbd89bdd8,0xbddf3d7c,0xbd443ded,0x3de73d5b,0xbd38bdef,0xbdf33d21,0xbd8e3dd5,0x3dce3d98,0xbcafbdfc,0xbdfe3c7b,
0x3d71bde2,0x3df83cf9,0xbd9dbdca,0xbdea3d4f,0xbdd53d8e,0x3d2c3df1,0x3d21bdf3,0xbdd8bd89,0xbdedbd44,0xbd983dce,0x3df7bd09,0xbb49be00,0xbcc8bdfb,0xbe00bbc9,0x3dc23da7,0x3dd1bd93,
0x3dc6bda2,0x3de73d5b,0xbd89bdd8,0xbdfe3c7b,0xbdfbbcc8,0xbd983dce,0x3defbd38,0x3c17bdff,0x3d44bded,0xbdacbdbe,0x3caf3dfc,0x3df73d09,0x3dd53d8e,0x3ddcbd84,0xbe00bb49,0xbd663de5,
0x3df5bd15,0x3dce3d98,0xbd66bde5,0xbdfcbcaf,0xbd8ebdd5,0xbe00bbc9,0x3ddf3d7c,0x3deabd4f,0x3ded3d44,0x3ddcbd84,0xbdff3c17,0xbd893dd8,0xbdfb3cc8,0xbd5b3de7,0x3dcabd9d,0xbb49be00,
0x3dff3c49,0x3dac3dbe,0xbd38bdef,0xbde5bd66,0x3cc8bdfb,0xbd84bddc,0x3caf3dfc,0x3dca3d9d,0xbd443ded,0x3d2c3df1,0x3b49be00,0xbda7bdc2,0x3d8ebdd5,0xbc96bdfd,0xbce03dfa,0x3d7c3ddf,
0x3de23d71,0x3d843ddc,0xbd09bdf7,0xbdb9bdb1,0x3dd5bd8e,0x3d5bbde7,0xbda73dc2,0xbcaf3dfc,0xbdedbd44,0xbdfd3c96,0x3dfe3c7b,0x3deabd4f,0x3cc83dfb,0x3dac3dbe,0xbd66bde5,0xbdd8bd89,
0x3da23dc6,0x3d2c3df1,0xbcafbdfc,0xbd7cbddf,0x3dfb3cc8,0x3dfdbc96,0xbe00bb49,0xbdf33d21,0x3d44bded,0x3bc9be00,0xbce03dfa,0x3c7b3dfe,0xbdd5bd8e,0xbdf8bcf9,0x3dea3d4f,0x3dff3c17,
0x3d153df5,0x3c963dfd,0xbc17bdff,0xbce0bdfa,0x3d8e3dd5,0x3dac3dbe,0xbd9dbdca,0xbdb9bdb1,0x3ded3d44,0x3df83cf9,0xbdf3bd21,0xbdfcbcaf,0x3dfbbcc8,0x3df1bd2c,0xbdf73d09,0xbdea3d4f,
0xbdb53d80,0xbdbe3dac,0xbdb93db1,0xbdc23da7,0xbd153df5,0xbddc3d84,0xbdd83d89,0xbddf3d7c,0xbd713de2,0xbdf13d2c,0xbdef3d38,0xbdf33d21,0xbda23dc6,0xbdfd3c96,0xbdfc3caf,0xbdfe3c7b,
0x3db53d80,0x3ddcbd84,0x3dcabd9d,0x3deabd4f,0xbdff3c49,0x3de73d5b,0x3df33d21,0x3dd83d89,0xbda2bdc6,0x3c963dfd,0x3d093df7,0x3b493e00,0x3d15bdf5,0xbdbe3dac,0xbda73dc2,0xbdd13d93,
0xbdb53d80,0xbdf13d2c,0xbdd83d89,0xbdfe3c7b,0xbd71bde2,0xbc96bdfd,0xbd38bdef,0x3c17bdff,0x3df5bd15,0x3e003bc9,0x3dfcbcaf,0x3df73d09,0x3c493dff,0xbcf93df8,0xbb493e00,0xbd663de5,
0x3db53d80,0x3dfdbc96,0x3de5bd66,0x3dfc3caf,0x3da2bdc6,0xbdbe3dac,0xbd7c3ddf,0xbdea3d4f,0xbc493dff,0x3cf9bdf8,0xbc17bdff,0x3d89bdd8,0xbd71bde2,0x3d2c3df1,0x3d9d3dca,0x3b493e00,
0xbdb53d80,0xbe00bbc9,0xbdef3d38,0xbde5bd66,0x3df53d15,0x3df83cf9,0x3dfcbcaf,0x3dca3d9d,0xbde2bd71,0xbde7bd5b,0xbe00bb49,0xbda7bdc2,0x3dc63da2,0x3dce3d98,0x3dfa3ce0,0x3d7c3ddf,
0x3db53d80,0x3df83cf9,0x3df7bd09,0x3db93db1,0x3c493dff,0xbd2cbdf1,0xbdc2bda7,0x3cafbdfc,0x3dc6bda2,0xbd983dce,0xbc7b3dfe,0xbdea3d4f,0xbdf5bd15,0x3e003bc9,0x3de5bd66,0x3dd83d89,
0xbdb53d80,0xbde7bd5b,0xbdfc3caf,0xbd7cbddf,0xbde23d71,0xbd983dce,0xbb493e00,0xbdf33d21,0x3d153df5,0x3dac3dbe,0x3dfa3ce0,0x3c7b3dfe,0x3dffbc49,0x3ddcbd84,0x3d4fbdea,0x3dff3c17,
0x3db53d80,0x3dce3d98,0x3dffbc17,0x3ce03dfa,0xbdc6bda2,0x3e003bc9,0x3dcabd9d,0x3db93db1,0xbdffbc49,0x3ddcbd84,0x3d21bdf3,0x3dfc3caf,0xbde23d71,0x3d5bbde7,0xbd09bdf7,0x3deabd4f,
0xbdb53d80,0xbdacbdbe,0xbe00bb49,0x3c17bdff,0x3d15bdf5,0xbd84bddc,0xbdfabce0,0x3d09bdf7,0x3d71bde2,0xbd2cbdf1,0xbdeabd4f,0x3d66bde5,0x3da2bdc6,0xbc96bdfd,0xbdd1bd93,0x3d9dbdca,
0x3db53d80,0x3d843ddc,0x3dfe3c7b,0xbd383def,0x3dffbc49,0xbd5b3de7,0x3d663de5,0xbdfa3ce0,0x3da23dc6,0xbdfd3c96,0xbd7c3ddf,0xbdb9bdb1,0xbd153df5,0xbdacbdbe,0xbdff3c17,0x3cafbdfc,
0xbdb53d80,0xbd2cbdf1,0xbdfabce0,0x3d9dbdca,0x3d713de2,0x3dfdbc96,0x3d4fbdea,0x3da73dc2,0xbdf53d15,0xbbc93e00,0x3dd13d93,0xbddf3d7c,0xbc49bdff,0xbdf8bcf9,0xbdb93db1,0xbd21bdf3,
0x3db53d80,0x3c963dfd,0x3df33d21,0xbdd13d93,0xbda23dc6,0xbdacbdbe,0xbdf73d09,0x3d38bdef,0x3c49bdff,0x3df83cf9,0x3da7bdc2,0x3ce03dfa,0x3d713de2,0xbdf13d2c,0xbc7b3dfe,0xbdb9bdb1,
0xbdb53d80,0x3bc9be00,0xbdeabd4f,0x3df3bd21,0xbdf5bd15,0xbcf93df8,0x3dd13d93,0xbdfe3c7b,0x3de23d71,0x3d5bbde7,0xbdb1bdb9,0x3dff3c17,0xbdc6bda2,0xbd983dce,0x3d893dd8,0xbdf7bd09,
0x3db53d80,0xbcf93df8,0x3ddf3d7c,0xbe003b49,0xbc49bdff,0x3df1bd2c,0xbc17bdff,0x3d933dd1,0xbdc63da2,0xbdcebd98,0xbdca3d9d,0x3d38bdef,0x3df53d15,0xbbc93e00,0x3df33d21,0xbdfa3ce0,
0xbdb53d80,0x3d5bbde7,0xbdd1bd93,0x3df73d09,0x3de2bd71,0xbdcebd98,0xbdb93db1,0x3d66bde5,0xbd15bdf5,0xbdbe3dac,0x3d893dd8,0xbdcabd9d,0xbdff3c49,0x3d843ddc,0x3defbd38,0xbdc23da7,
0x3db53d80,0xbd983dce,0x3dc23da7,0xbdd8bd89,0x3dc63da2,0xbbc93e00,0x3dfe3c7b,0xbe003b49,0x3dff3c49,0x3d843ddc,0x3de5bd66,0xbdd13d93,0x3de2bd71,0x3de73d5b,0x3d7cbddf,0xbd383def,
0xbdb53d80,0x3dbebdac,0xbdb1bdb9,0x3da73dc2,0xbd153df5,0x3ddcbd84,0xbd89bdd8,0x3d7c3ddf,0xbd713de2,0x3df1bd2c,0xbd38bdef,0x3d213df3,0xbda23dc6,0x3dfdbc96,0xbcafbdfc,0x3c7b3dfe,
0x3db53d80,0xbddc3d84,0x3d9d3dca,0xbd4fbdea,0xbdff3c49,0xbde7bd5b,0xbd213df3,0x3d89bdd8,0xbda2bdc6,0xbc96bdfd,0xbdf73d09,0x3e00bb49,0x3d15bdf5,0x3dbebdac,0xbdc2bda7,0x3d933dd1,
0xbdb53d80,0x3df1bd2c,0xbd89bdd8,0x3c7b3dfe,0xbd71bde2,0x3c963dfd,0x3defbd38,0xbdffbc17,0x3df5bd15,0xbe00bbc9,0x3caf3dfc,0x3d09bdf7,0x3c493dff,0x3cf9bdf8,0xbe00bb49,0x3de53d66,
0x3db53d80,0xbdfd3c96,0x3d663de5,0x3cafbdfc,0x3da2bdc6,0x3dbebdac,0xbddfbd7c,0x3d4f3dea,0xbc493dff,0xbcf93df8,0x3dffbc17,0xbdd8bd89,0xbd71bde2,0xbd2cbdf1,0xbdca3d9d,0x3e00bb49,
0xbdb53d80,0x3e003bc9,0xbd38bdef,0xbd663de5,0x3df53d15,0xbdf8bcf9,0x3caf3dfc,0x3d9dbdca,0xbde2bd71,0x3de73d5b,0x3b49be00,0xbdc23da7,0x3dc63da2,0xbdcebd98,0xbce03dfa,0x3ddfbd7c,
0x3db53d80,0xbdf8bcf9,0x3d093df7,0x3db1bdb9,0x3c493dff,0x3d2c3df1,0x3da7bdc2,0xbdfcbcaf,0x3dc6bda2,0x3d98bdce,0xbdfebc7b,0x3d4f3dea,0xbdf5bd15,0xbe00bbc9,0x3d663de5,0x3d89bdd8,
0xbdb53d80,0x3de73d5b,0xbcafbdfc,0xbddf3d7c,0xbde23d71,0x3d98bdce,0xbe00bb49,0x3d213df3,0x3d153df5,0xbdacbdbe,0xbce03dfa,0x3dfebc7b,0x3dffbc49,0xbddc3d84,0x3dea3d4f,0x3c17bdff,
0x3db53d80,0xbdcebd98,0x3c173dff,0x3dfabce0,0xbdc6bda2,0xbe00bbc9,0x3d9d3dca,0x3db1bdb9,0xbdffbc49,0xbddc3d84,0x3df33d21,0x3cafbdfc,0xbde23d71,0xbd5b3de7,0x3df7bd09,0xbd4fbdea,
0xbdb53d80,0x3dac3dbe,0x3b49be00,0xbdffbc17,0x3d15bdf5,0x3d843ddc,0x3ce0bdfa,0xbdf7bd09,0x3d71bde2,0x3d2c3df1,0x3d4fbdea,0xbde5bd66,0x3da2bdc6,0x3c963dfd,0x3d93bdd1,0xbdcabd9d,
0x3db53d80,0xbd84bddc,0xbc7b3dfe,0x3def3d38,0x3dffbc49,0x3d5bbde7,0xbde53d66,0x3ce03dfa,0x3da23dc6,0x3dfdbc96,0xbddfbd7c,0xbdb13db9,0xbd153df5,0x3dac3dbe,0xbc17bdff,0xbdfcbcaf,
0xbdb53d80,0x3d2c3df1,0x3ce0bdfa,0xbdcabd9d,0x3d713de2,0xbdfd3c96,0x3dea3d4f,0x3dc2bda7,0xbdf53d15,0x3bc9be00,0xbd933dd1,0x3d7c3ddf,0xbc49bdff,0x3df83cf9,0xbdb1bdb9,0xbdf33d21,
0x3db53d80,0xbc96bdfd,0xbd213df3,0x3d933dd1,0xbda23dc6,0x3dac3dbe,0xbd09bdf7,0xbdefbd38,0x3c49bdff,0xbdf8bcf9,0x3dc23da7,0x3dfabce0,0x3d713de2,0x3df1bd2c,0xbdfebc7b,0xbdb13db9,
0xbdb53d80,0xbbc93e00,0x3d4fbdea,0xbd21bdf3,0xbdf5bd15,0x3cf9bdf8,0xbd933dd1,0x3c7b3dfe,0x3de23d71,0xbd5b3de7,0x3db9bdb1,0x3c17bdff,0xbdc6bda2,0x3d98bdce,0xbdd83d89,0xbd093df7,
0x3db53d80,0x3cf9bdf8,0xbd7c3ddf,0x3b493e00,0xbc49bdff,0xbdf13d2c,0x3dffbc17,0x3dd1bd93,0xbdc63da2,0x3dce3d98,0xbd9dbdca,0xbdefbd38,0x3df53d15,0x3bc9be00,0xbd213df3,0x3ce03dfa,
0xbdb53d80,0xbd5b3de7,0x3d93bdd1,0x3d09bdf7,0x3de2bd71,0x3dce3d98,0xbdb1bdb9,0xbde5bd66,0xbd15bdf5,0x3dbebdac,0xbdd83d89,0xbd9d3dca,0xbdff3c49,0xbd84bddc,0x3d383def,0x3da73dc2,
0x3db53d80,0x3d98bdce,0xbda73dc2,0xbd893dd8,0x3dc63da2,0x3bc9be00,0xbc7b3dfe,0x3b493e00,0x3dff3c49,0xbd84bddc,0x3d663de5,0x3d933dd1,0x3de2bd71,0xbde7bd5b,0x3ddf3d7c,0x3def3d38,
0xbcc83dfb,0xbc493dff,0xbbc93e00,0xbc963dfd,0xbd443ded,0xbd713de2,0xbd5b3de7,0xbd843ddc,0xbdb53db5,0xbdc63da2,0xbdbe3dac,0xbdce3d98,0xbded3d44,0xbdf53d15,0xbdf13d2c,0xbdf83cf9,
0xbd8e3dd5,0xbd153df5,0xbc963dfd,0xbd5b3de7,0xbded3d44,0xbdff3c49,0xbdf83cf9,0xbe00bbc9,0xbdb5bdb5,0xbd71bde2,0xbd98bdce,0xbd2cbdf1,0x3d44bded,0x3da2bdc6,0x3d84bddc,0x3dbebdac,
0xbdd53d8e,0xbd713de2,0xbcf93df8,0xbdac3dbe,0xbdedbd44,0xbda2bdc6,0xbdcebd98,0xbd5bbde7,0x3db5bdb5,0x3df5bd15,0x3ddcbd84,0x3e00bbc9,0x3d443ded,0xbc493dff,0x3c963dfd,0xbd2c3df1,
0xbdfb3cc8,0xbda23dc6,0xbd2c3df1,0xbddc3d84,0xbd44bded,0x3d15bdf5,0xbbc9be00,0x3d98bdce,0x3db53db5,0x3c493dff,0x3d5b3de7,0xbcf93df8,0xbdedbd44,0xbd71bde2,0xbdbebdac,0xbc96bdfd,
0xbdfbbcc8,0xbdc63da2,0xbd5b3de7,0xbdf83cf9,0x3d44bded,0x3df5bd15,0x3dbebdac,0x3dfd3c96,0xbdb53db5,0xbdffbc49,0xbdf13d2c,0xbddcbd84,0x3dedbd44,0x3de23d71,0x3e003bc9,0x3d983dce,
0xbdd5bd8e,0xbde23d71,0xbd843ddc,0xbe00bbc9,0x3dedbd44,0x3dc63da2,0x3dfd3c96,0x3d2c3df1,0xbdb5bdb5,0x3d15bdf5,0xbcf9bdf8,0x3dbebdac,0xbd443ded,0xbdff3c49,0xbdce3d98,0xbde7bd5b,
0xbd8ebdd5,0xbdf53d15,0xbd983dce,0xbdf1bd2c,0x3ded3d44,0xbc493dff,0x3d843ddc,0xbdac3dbe,0x3db5bdb5,0x3de23d71,0x3dfdbc96,0x3d5b3de7,0xbd44bded,0x3dc6bda2,0x3cf9bdf8,0x3e00bbc9,
0xbcc8bdfb,0xbdff3c49,0xbdac3dbe,0xbdcebd98,0x3d443ded,0xbde23d71,0xbd2c3df1,0xbdf8bcf9,0x3db53db5,0xbda23dc6,0x3bc93e00,0xbdfd3c96,0x3ded3d44,0xbd153df5,0x3d5b3de7,0xbddc3d84,
0x3cc8bdfb,0xbdffbc49,0xbdbe3dac,0xbd98bdce,0xbd443ded,0xbde2bd71,0xbdf13d2c,0xbcf9bdf8,0xbdb53db5,0xbda2bdc6,0xbe00bbc9,0x3c96bdfd,0xbded3d44,0xbd15bdf5,0xbde7bd5b,0x3d84bddc,
0x3d8ebdd5,0xbdf5bd15,0xbdce3d98,0xbd2cbdf1,0xbded3d44,0xbc49bdff,0xbddcbd84,0x3dbebdac,0xbdb5bdb5,0x3de2bd71,0x3c96bdfd,0x3de73d5b,0x3d44bded,0x3dc63da2,0x3df8bcf9,0xbbc93e00,
0x3dd5bd8e,0xbde2bd71,0xbddc3d84,0xbbc9be00,0xbdedbd44,0x3dc6bda2,0xbc96bdfd,0x3df13d2c,0x3db5bdb5,0x3d153df5,0x3df83cf9,0xbdac3dbe,0x3d443ded,0xbdffbc49,0xbd983dce,0xbd5bbde7,
0x3dfbbcc8,0xbdc6bda2,0xbde73d5b,0x3cf9bdf8,0xbd44bded,0x3df53d15,0x3dacbdbe,0x3c963dfd,0x3db53db5,0xbdff3c49,0xbd2c3df1,0xbd84bddc,0xbdedbd44,0x3de2bd71,0xbbc9be00,0x3dce3d98,
0x3dfb3cc8,0xbda2bdc6,0xbdf13d2c,0x3d84bddc,0x3d44bded,0x3d153df5,0x3e003bc9,0xbdce3d98,0xbdb53db5,0x3c49bdff,0xbde7bd5b,0x3df8bcf9,0x3dedbd44,0xbd713de2,0x3dac3dbe,0xbdfdbc96,
0x3dd53d8e,0xbd71bde2,0xbdf83cf9,0x3dbebdac,0x3dedbd44,0xbda23dc6,0x3d983dce,0xbde7bd5b,0xbdb5bdb5,0x3df53d15,0x3d84bddc,0xbbc93e00,0xbd443ded,0xbc49bdff,0xbdfdbc96,0x3df1bd2c,
0x3d8e3dd5,0xbd15bdf5,0xbdfd3c96,0x3de7bd5b,0x3ded3d44,0xbdffbc49,0xbcf93df8,0xbbc9be00,0x3db5bdb5,0xbd713de2,0x3dce3d98,0xbdf1bd2c,0xbd44bded,0x3da23dc6,0x3ddcbd84,0xbdac3dbe,
0x3cc83dfb,0xbc49bdff,0xbe003bc9,0x3dfdbc96,0x3d443ded,0xbd71bde2,0xbde73d5b,0x3ddcbd84,0x3db53db5,0xbdc6bda2,0xbdac3dbe,0x3d98bdce,0x3ded3d44,0xbdf5bd15,0xbd2c3df1,0x3cf9bdf8,
0xbcc83dfb,0x3c49bdff,0xbe00bbc9,0x3dfd3c96,0xbd443ded,0x3d71bde2,0xbde7bd5b,0x3ddc3d84,0xbdb53db5,0x3dc6bda2,0xbdacbdbe,0x3d983dce,0xbded3d44,0x3df5bd15,0xbd2cbdf1,0x3cf93df8,
0xbd8e3dd5,0x3d15bdf5,0xbdfdbc96,0x3de73d5b,0xbded3d44,0x3dffbc49,0xbcf9bdf8,0xbbc93e00,0xbdb5bdb5,0x3d713de2,0x3dcebd98,0xbdf13d2c,0x3d44bded,0xbda23dc6,0x3ddc3d84,0xbdacbdbe,
0xbdd53d8e,0x3d71bde2,0xbdf8bcf9,0x3dbe3dac,0xbdedbd44,0x3da23dc6,0x3d98bdce,0xbde73d5b,0x3db5bdb5,0xbdf53d15,0x3d843ddc,0xbbc9be00,0x3d443ded,0x3c49bdff,0xbdfd3c96,0x3df13d2c,
0xbdfb3cc8,0x3da2bdc6,0xbdf1bd2c,0x3d843ddc,0xbd44bded,0xbd153df5,0x3e00bbc9,0xbdcebd98,0x3db53db5,0xbc49bdff,0xbde73d5b,0x3df83cf9,0xbdedbd44,0x3d713de2,0x3dacbdbe,0xbdfd3c96,
0xbdfbbcc8,0x3dc6bda2,0xbde7bd5b,0x3cf93df8,0x3d44bded,0xbdf53d15,0x3dac3dbe,0x3c96bdfd,0xbdb53db5,0x3dff3c49,0xbd2cbdf1,0xbd843ddc,0x3dedbd44,0xbde2bd71,0xbbc93e00,0x3dcebd98,
0xbdd5bd8e,0x3de2bd71,0xbddcbd84,0xbbc93e00,0x3dedbd44,0xbdc6bda2,0xbc963dfd,0x3df1bd2c,0xbdb5bdb5,0xbd153df5,0x3df8bcf9,0xbdacbdbe,0xbd443ded,0x3dffbc49,0xbd98bdce,0xbd5b3de7,
0xbd8ebdd5,0x3df5bd15,0xbdcebd98,0xbd2c3df1,0x3ded3d44,0x3c49bdff,0xbddc3d84,0x3dbe3dac,0x3db5bdb5,0xbde2bd71,0x3c963dfd,0x3de7bd5b,0xbd44bded,0xbdc63da2,0x3df83cf9,0xbbc9be00,
0xbcc8bdfb,0x3dffbc49,0xbdbebdac,0xbd983dce,0x3d443ded,0x3de2bd71,0xbdf1bd2c,0xbcf93df8,0x3db53db5,0x3da2bdc6,0xbe003bc9,0x3c963dfd,0x3ded3d44,0x3d15bdf5,0xbde73d5b,0x3d843ddc,
0x3cc8bdfb,0x3dff3c49,0xbdacbdbe,0xbdce3d98,0xbd443ded,0x3de23d71,0xbd2cbdf1,0xbdf83cf9,0xbdb53db5,0x3da23dc6,0x3bc9be00,0xbdfdbc96,0xbded3d44,0x3d153df5,0x3d5bbde7,0xbddcbd84,
0x3d8ebdd5,0x3df53d15,0xbd98bdce,0xbdf13d2c,0xbded3d44,0x3c493dff,0x3d84bddc,0xbdacbdbe,0xbdb5bdb5,0xbde23d71,0x3dfd3c96,0x3d5bbde7,0x3d44bded,0xbdc6bda2,0x3cf93df8,0x3e003bc9,
0x3dd5bd8e,0x3de23d71,0xbd84bddc,0xbe003bc9,0xbdedbd44,0xbdc63da2,0x3dfdbc96,0x3d2cbdf1,0x3db5bdb5,0xbd15bdf5,0xbcf93df8,0x3dbe3dac,0x3d443ded,0x3dff3c49,0xbdcebd98,0xbde73d5b,
0x3dfbbcc8,0x3dc63da2,0xbd5bbde7,0xbdf8bcf9,0xbd44bded,0xbdf5bd15,0x3dbe3dac,0x3dfdbc96,0x3db53db5,0x3dffbc49,0xbdf1bd2c,0xbddc3d84,0xbdedbd44,0xbde23d71,0x3e00bbc9,0x3d98bdce,
0x3dfb3cc8,0x3da23dc6,0xbd2cbdf1,0xbddcbd84,0x3d44bded,0xbd15bdf5,0xbbc93e00,0x3d983dce,0xbdb53db5,0xbc493dff,0x3d5bbde7,0xbcf9bdf8,0x3dedbd44,0x3d71bde2,0xbdbe3dac,0xbc963dfd,
0x3dd53d8e,0x3d713de2,0xbcf9bdf8,0xbdacbdbe,0x3dedbd44,0x3da2bdc6,0xbdce3d98,0xbd5b3de7,0xbdb5bdb5,0xbdf5bd15,0x3ddc3d84,0x3e003bc9,0xbd443ded,0x3c493dff,0x3c96bdfd,0xbd2cbdf1,
0x3d8e3dd5,0x3d153df5,0xbc96bdfd,0xbd5bbde7,0x3ded3d44,0x3dff3c49,0xbdf8bcf9,0xbe003bc9,0x3db5bdb5,0x3d71bde2,0xbd983dce,0xbd2c3df1,0xbd44bded,0xbda2bdc6,0x3d843ddc,0x3dbe3dac,
0x3cc83dfb,0x3c493dff,0xbbc9be00,0xbc96bdfd,0x3d443ded,0x3d713de2,0xbd5bbde7,0xbd84bddc,0x3db53db5,0x3dc63da2,0xbdbebdac,0xbdcebd98,0x3ded3d44,0x3df53d15,0xbdf1bd2c,0xbdf8bcf9,
0xbd803d80,0xbdffbc49,0xbe00bbc9,0xbdfdbc96,0xbd8e3dd5,0xbde2bd71,0xbde7bd5b,0xbddcbd84,0xbdd53d8e,0xbda2bdc6,0xbdacbdbe,0xbd98bdce,0xbdfb3cc8,0xbd15bdf5,0xbd2cbdf1,0xbcf9bdf8,
0x3d803d80,0x3df53d15,0x3dfd3c96,0x3de73d5b,0xbdfbbcc8,0x3c493dff,0x3cf93df8,0xbbc93e00,0xbcc8bdfb,0xbde23d71,0xbdce3d98,0xbdf13d2c,0x3dd5bd8e,0xbdc6bda2,0xbddcbd84,0xbdacbdbe,
0xbd803d80,0xbde2bd71,0xbdf8bcf9,0xbdbebdac,0xbcc8bdfb,0x3dc6bda2,0x3d98bdce,0x3de7bd5b,0x3dfb3cc8,0x3d153df5,0x3d843ddc,0x3bc93e00,0xbd8e3dd5,0xbdffbc49,0xbdfd3c96,0xbdf1bd2c,
0x3d803d80,0x3dc63da2,0x3df13d2c,0x3d843ddc,0x3dd5bd8e,0xbdf5bd15,0xbe003bc9,0xbdcebd98,0xbd8e3dd5,0x3dffbc49,0x3de7bd5b,0x3df83cf9,0x3cc8bdfb,0xbde23d71,0xbdac3dbe,0xbdfd3c96,
0xbd803d80,0xbda2bdc6,0xbde7bd5b,0xbcf9bdf8,0x3dd53d8e,0x3d153df5,0x3dac3dbe,0xbc963dfd,0xbd8ebdd5,0x3c49bdff,0xbd2cbdf1,0x3d84bddc,0x3cc83dfb,0xbd713de2,0xbbc93e00,0xbdce3d98,
0x3d803d80,0x3d713de2,0x3ddc3d84,0xbbc93e00,0xbcc83dfb,0x3da2bdc6,0x3c96bdfd,0x3df1bd2c,0x3dfbbcc8,0xbdf5bd15,0xbdf83cf9,0xbdacbdbe,0xbd8ebdd5,0x3c493dff,0x3d983dce,0xbd5b3de7,
0xbd803d80,0xbd15bdf5,0xbdcebd98,0x3d2cbdf1,0xbdfb3cc8,0xbdffbc49,0xbddc3d84,0xbdbebdac,0xbcc83dfb,0xbd713de2,0x3c963dfd,0xbde73d5b,0x3dd53d8e,0x3da23dc6,0x3df83cf9,0x3bc93e00,
0x3d803d80,0x3c493dff,0x3dbe3dac,0xbd983dce,0xbd8ebdd5,0x3d713de2,0x3df13d2c,0xbcf93df8,0xbdd5bd8e,0x3dc63da2,0x3e00bbc9,0x3c963dfd,0xbdfbbcc8,0x3df53d15,0x3de7bd5b,0x3d843ddc,
0xbd803d80,0x3c49bdff,0xbdacbdbe,0x3dcebd98,0x3d8ebdd5,0x3d71bde2,0xbd2cbdf1,0x3df8bcf9,0x3dd5bd8e,0x3dc6bda2,0x3bc9be00,0x3dfd3c96,0x3dfbbcc8,0x3df5bd15,0x3d5bbde7,0x3ddc3d84,
0x3d803d80,0xbd153df5,0x3d983dce,0xbdf13d2c,0x3dfb3cc8,0xbdff3c49,0xbd843ddc,0xbdacbdbe,0x3cc83dfb,0xbd71bde2,0xbdfdbc96,0x3d5bbde7,0xbdd53d8e,0x3da2bdc6,0xbcf9bdf8,0x3e003bc9,
0xbd803d80,0x3d71bde2,0xbd84bddc,0x3e00bbc9,0x3cc83dfb,0x3da23dc6,0x3dfdbc96,0xbd2c3df1,0xbdfbbcc8,0xbdf53d15,0xbcf93df8,0xbdbebdac,0x3d8ebdd5,0x3c49bdff,0xbdcebd98,0x3de7bd5b,
0x3d803d80,0xbda23dc6,0x3d5b3de7,0xbdf8bcf9,0xbdd53d8e,0x3d15bdf5,0xbdbebdac,0x3dfdbc96,0x3d8ebdd5,0x3c493dff,0x3df13d2c,0xbddc3d84,0xbcc83dfb,0xbd71bde2,0xbe003bc9,0x3d98bdce,
0xbd803d80,0x3dc6bda2,0xbd2cbdf1,0x3ddc3d84,0xbdd5bd8e,0xbdf53d15,0xbbc93e00,0xbd98bdce,0x3d8e3dd5,0x3dff3c49,0x3d5bbde7,0x3cf93df8,0xbcc8bdfb,0xbde2bd71,0xbdbe3dac,0x3c96bdfd,
0x3d803d80,0xbde23d71,0x3cf93df8,0xbdacbdbe,0x3cc8bdfb,0x3dc63da2,0x3dcebd98,0xbd5b3de7,0xbdfb3cc8,0x3d15bdf5,0xbddcbd84,0x3e003bc9,0x3d8e3dd5,0xbdff3c49,0xbc963dfd,0xbd2cbdf1,
0xbd803d80,0x3df5bd15,0xbc96bdfd,0x3d5b3de7,0x3dfbbcc8,0x3c49bdff,0xbdf8bcf9,0x3e00bbc9,0x3cc8bdfb,0xbde2bd71,0xbd983dce,0x3d2cbdf1,0xbdd5bd8e,0xbdc63da2,0x3d843ddc,0xbdbebdac,
0x3d803d80,0xbdff3c49,0x3bc93e00,0xbc96bdfd,0x3d8e3dd5,0xbde23d71,0x3d5b3de7,0xbd84bddc,0x3dd53d8e,0xbda23dc6,0x3dbe3dac,0xbdcebd98,0x3dfb3cc8,0xbd153df5,0x3df13d2c,0xbdf8bcf9,
0xbd803d80,0x3dff3c49,0x3bc9be00,0xbc963dfd,0xbd8e3dd5,0x3de23d71,0x3d5bbde7,0xbd843ddc,0xbdd53d8e,0x3da23dc6,0x3dbebdac,0xbdce3d98,0xbdfb3cc8,0x3d153df5,0x3df1bd2c,0xbdf83cf9,
0x3d803d80,0xbdf5bd15,0xbc963dfd,0x3d5bbde7,0xbdfbbcc8,0xbc49bdff,0xbdf83cf9,0x3e003bc9,0xbcc8bdfb,0x3de2bd71,0xbd98bdce,0x3d2c3df1,0x3dd5bd8e,0x3dc63da2,0x3d84bddc,0xbdbe3dac,
0xbd803d80,0x3de23d71,0x3cf9bdf8,0xbdac3dbe,0xbcc8bdfb,0xbdc63da2,0x3dce3d98,0xbd5bbde7,0x3dfb3cc8,0xbd15bdf5,0xbddc3d84,0x3e00bbc9,0xbd8e3dd5,0x3dff3c49,0xbc96bdfd,0xbd2c3df1,
0x3d803d80,0xbdc6bda2,0xbd2c3df1,0x3ddcbd84,0x3dd5bd8e,0x3df53d15,0xbbc9be00,0xbd983dce,0xbd8e3dd5,0xbdff3c49,0x3d5b3de7,0x3cf9bdf8,0x3cc8bdfb,0x3de2bd71,0xbdbebdac,0x3c963dfd,
0xbd803d80,0x3da23dc6,0x3d5bbde7,0xbdf83cf9,0x3dd53d8e,0xbd15bdf5,0xbdbe3dac,0x3dfd3c96,0xbd8ebdd5,0xbc493dff,0x3df1bd2c,0xbddcbd84,0x3cc83dfb,0x3d71bde2,0xbe00bbc9,0x3d983dce,
0x3d803d80,0xbd71bde2,0xbd843ddc,0x3e003bc9,0xbcc83dfb,0xbda23dc6,0x3dfd3c96,0xbd2cbdf1,0x3dfbbcc8,0x3df53d15,0xbcf9bdf8,0xbdbe3dac,0xbd8ebdd5,0xbc49bdff,0xbdce3d98,0x3de73d5b,
0xbd803d80,0x3d153df5,0x3d98bdce,0xbdf1bd2c,0xbdfb3cc8,0x3dff3c49,0xbd84bddc,0xbdac3dbe,0xbcc83dfb,0x3d71bde2,0xbdfd3c96,0x3d5b3de7,0x3dd53d8e,0xbda2bdc6,0xbcf93df8,0x3e00bbc9,
0x3d803d80,0xbc49bdff,0xbdac3dbe,0x3dce3d98,0xbd8ebdd5,0xbd71bde2,0xbd2c3df1,0x3df83cf9,0xbdd5bd8e,0xbdc6bda2,0x3bc93e00,0x3dfdbc96,0xbdfbbcc8,0xbdf5bd15,0x3d5b3de7,0x3ddcbd84,
0xbd803d80,0xbc493dff,0x3dbebdac,0xbd98bdce,0x3d8ebdd5,0xbd713de2,0x3df1bd2c,0xbcf9bdf8,0x3dd5bd8e,0xbdc63da2,0x3e003bc9,0x3c96bdfd,0x3dfbbcc8,0xbdf53d15,0x3de73d5b,0x3d84bddc,
0x3d803d80,0x3d15bdf5,0xbdce3d98,0x3d2c3df1,0x3dfb3cc8,0x3dffbc49,0xbddcbd84,0xbdbe3dac,0x3cc83dfb,0x3d713de2,0x3c96bdfd,0xbde7bd5b,0xbdd53d8e,0xbda23dc6,0x3df8bcf9,0x3bc9be00,
0xbd803d80,0xbd713de2,0x3ddcbd84,0xbbc9be00,0x3cc83dfb,0xbda2bdc6,0x3c963dfd,0x3df13d2c,0xbdfbbcc8,0x3df5bd15,0xbdf8bcf9,0xbdac3dbe,0x3d8ebdd5,0xbc493dff,0x3d98bdce,0xbd5bbde7,
0x3d803d80,0x3da2bdc6,0xbde73d5b,0xbcf93df8,0xbdd53d8e,0xbd153df5,0x3dacbdbe,0xbc96bdfd,0x3d8ebdd5,0xbc49bdff,0xbd2c3df1,0x3d843ddc,0xbcc83dfb,0x3d713de2,0xbbc9be00,0xbdcebd98,
0xbd803d80,0xbdc63da2,0x3df1bd2c,0x3d84bddc,0xbdd5bd8e,0x3df5bd15,0xbe00bbc9,0xbdce3d98,0x3d8e3dd5,0xbdffbc49,0x3de73d5b,0x3df8bcf9,0xbcc8bdfb,0x3de23d71,0xbdacbdbe,0xbdfdbc96,
0x3d803d80,0x3de2bd71,0xbdf83cf9,0xbdbe3dac,0x3cc8bdfb,0xbdc6bda2,0x3d983dce,0x3de73d5b,0xbdfb3cc8,0xbd153df5,0x3d84bddc,0x3bc9be00,0x3d8e3dd5,0x3dffbc49,0xbdfdbc96,0xbdf13d2c,
0xbd803d80,0xbdf53d15,0x3dfdbc96,0x3de7bd5b,0x3dfbbcc8,0xbc493dff,0x3cf9bdf8,0xbbc9be00,0x3cc8bdfb,0x3de23d71,0xbdcebd98,0xbdf1bd2c,0xbdd5bd8e,0x3dc6bda2,0xbddc3d84,0xbdac3dbe,
0x3d803d80,0x3dffbc49,0xbe003bc9,0xbdfd3c96,0x3d8e3dd5,0x3de2bd71,0xbde73d5b,0xbddc3d84,0x3dd53d8e,0x3da2bdc6,0xbdac3dbe,0xbd983dce,0x3dfb3cc8,0x3d15bdf5,0xbd2c3df1,0xbcf93df8,
0xbd153df5,0xbc963dfd,0xbc173dff,0xbce03dfa,0xbd8e3dd5,0xbdac3dbe,0xbd9d3dca,0xbdb93db1,0xbded3d44,0xbdf83cf9,0xbdf33d21,0xbdfc3caf,0xbdfbbcc8,0xbdf1bd2c,0xbdf7bd09,0xbdeabd4f,
0xbda23dc6,0xbd2c3df1,0xbcaf3dfc,0xbd7c3ddf,0xbdfb3cc8,0xbdfdbc96,0xbe003b49,0xbdf3bd21,0xbd44bded,0xbbc9be00,0xbce0bdfa,0x3c7bbdfe,0x3dd5bd8e,0x3df8bcf9,0x3deabd4f,0x3dffbc17,
0xbde23d71,0xbd843ddc,0xbd093df7,0xbdb93db1,0xbdd5bd8e,0xbd5bbde7,0xbda7bdc2,0xbcafbdfc,0x3dedbd44,0x3dfd3c96,0x3dfebc7b,0x3dea3d4f,0xbcc83dfb,0xbdac3dbe,0xbd663de5,0xbdd83d89,
0xbdff3c49,0xbdac3dbe,0xbd383def,0xbde53d66,0xbcc8bdfb,0x3d84bddc,0x3cafbdfc,0x3dcabd9d,0x3d443ded,0xbd2c3df1,0x3b493e00,0xbda73dc2,0xbd8ebdd5,0x3c96bdfd,0xbce0bdfa,0x3d7cbddf,
0xbdf5bd15,0xbdce3d98,0xbd663de5,0xbdfc3caf,0x3d8ebdd5,0x3e00bbc9,0x3ddfbd7c,0x3dea3d4f,0xbded3d44,0xbddcbd84,0xbdffbc17,0xbd89bdd8,0x3dfb3cc8,0x3d5b3de7,0x3dca3d9d,0xbb493e00,
0xbdc6bda2,0xbde73d5b,0xbd893dd8,0xbdfebc7b,0x3dfbbcc8,0x3d983dce,0x3def3d38,0x3c173dff,0xbd44bded,0x3dacbdbe,0x3cafbdfc,0x3df7bd09,0xbdd53d8e,0xbddcbd84,0xbe003b49,0xbd66bde5,
0xbd71bde2,0xbdf83cf9,0xbd9d3dca,0xbdeabd4f,0x3dd53d8e,0xbd2c3df1,0x3d213df3,0xbdd83d89,0x3dedbd44,0x3d983dce,0x3df73d09,0xbb493e00,0x3cc8bdfb,0x3e00bbc9,0x3dc2bda7,0x3dd13d93,
0xbc49bdff,0xbe003bc9,0xbdb13db9,0xbdc2bda7,0x3cc83dfb,0xbdf83cf9,0xbd893dd8,0xbddfbd7c,0x3d443ded,0xbde73d5b,0xbd383def,0xbdf3bd21,0x3d8e3dd5,0xbdce3d98,0xbcaf3dfc,0xbdfebc7b,
0x3d15bdf5,0xbdfdbc96,0xbdc23da7,0xbd89bdd8,0xbd8e3dd5,0xbdbebdac,0xbdfe3c7b,0x3b49be00,0xbded3d44,0xbcf9bdf8,0xbde5bd66,0x3d93bdd1,0xbdfbbcc8,0x3d2cbdf1,0xbd7cbddf,0x3defbd38,
0x3da2bdc6,0xbdf1bd2c,0xbdd13d93,0xbd09bdf7,0xbdfb3cc8,0x3c96bdfd,0xbdb9bdb1,0x3de5bd66,0xbd44bded,0x3e00bbc9,0x3d89bdd8,0x3d9d3dca,0x3dd5bd8e,0x3cf93df8,0x3def3d38,0xbda73dc2,
0x3de2bd71,0xbddcbd84,0xbddf3d7c,0x3b49be00,0xbdd5bd8e,0x3de7bd5b,0x3c17bdff,0x3dd13d93,0x3dedbd44,0xbc963dfd,0x3dca3d9d,0xbdef3d38,0xbcc83dfb,0xbdbebdac,0xbdf33d21,0x3ce0bdfa,
0x3dffbc49,0xbdbebdac,0xbdea3d4f,0x3d21bdf3,0xbcc8bdfb,0x3ddc3d84,0x3dd1bd93,0xbc7b3dfe,0x3d443ded,0xbdf1bd2c,0xbdb13db9,0xbc17bdff,0xbd8ebdd5,0x3dfd3c96,0x3d89bdd8,0x3d093df7,
0x3df53d15,0xbd98bdce,0xbdf33d21,0x3d93bdd1,0x3d8ebdd5,0x3bc93e00,0x3df73d09,0xbdef3d38,0xbded3d44,0x3d84bddc,0xbda7bdc2,0x3dfa3ce0,0x3dfb3cc8,0xbde73d5b,0x3c7b3dfe,0xbdb1bdb9,
0x3dc63da2,0xbd5bbde7,0xbdfa3ce0,0x3dcabd9d,0x3dfbbcc8,0xbdce3d98,0x3d4f3dea,0xbdc2bda7,0xbd44bded,0x3dbe3dac,0x3dd1bd93,0xbd7c3ddf,0xbdd53d8e,0x3d84bddc,0xbdb9bdb1,0x3df33d21,
0x3d713de2,0xbcf9bdf8,0xbdfe3c7b,0x3defbd38,0x3dd53d8e,0xbdf1bd2c,0xbd663de5,0x3ce0bdfa,0x3dedbd44,0xbdce3d98,0x3d7c3ddf,0xbdb1bdb9,0x3cc8bdfb,0x3bc93e00,0x3dff3c17,0xbdfc3caf,
0x3c493dff,0xbbc9be00,0xbe003b49,0x3dffbc17,0x3cc83dfb,0xbcf9bdf8,0xbdfa3ce0,0x3df7bd09,0x3d443ded,0xbd5bbde7,0xbdea3d4f,0x3de5bd66,0x3d8e3dd5,0xbd98bdce,0xbdd13d93,0x3dcabd9d,
0xbd153df5,0x3c96bdfd,0xbdffbc17,0x3dfa3ce0,0xbd8e3dd5,0x3dacbdbe,0xbdcabd9d,0x3db13db9,0xbded3d44,0x3df8bcf9,0xbd21bdf3,0x3caf3dfc,0xbdfbbcc8,0x3df13d2c,0x3d09bdf7,0xbd4f3dea,
0xbda23dc6,0x3d2cbdf1,0xbdfcbcaf,0x3ddf3d7c,0xbdfb3cc8,0x3dfd3c96,0xbb49be00,0xbd213df3,0xbd44bded,0x3bc93e00,0x3dfabce0,0xbdfebc7b,0x3dd5bd8e,0xbdf83cf9,0x3d4f3dea,0xbc17bdff,
0xbde23d71,0x3d84bddc,0xbdf7bd09,0x3db13db9,0xbdd5bd8e,0x3d5b3de7,0x3dc2bda7,0xbdfc3caf,0x3dedbd44,0xbdfdbc96,0x3c7b3dfe,0x3d4fbdea,0xbcc83dfb,0x3dacbdbe,0xbde5bd66,0x3d893dd8,
0xbdff3c49,0x3dacbdbe,0xbdefbd38,0x3d663de5,0xbcc8bdfb,0xbd843ddc,0x3dfc3caf,0xbd9dbdca,0x3d443ded,0x3d2cbdf1,0xbe003b49,0x3dc23da7,0xbd8ebdd5,0xbc963dfd,0x3dfabce0,0xbddfbd7c,
0xbdf5bd15,0x3dcebd98,0xbde5bd66,0x3caf3dfc,0x3d8ebdd5,0xbe003bc9,0x3d7c3ddf,0x3d4fbdea,0xbded3d44,0x3ddc3d84,0x3c17bdff,0xbdd83d89,0x3dfb3cc8,0xbd5bbde7,0xbd9d3dca,0x3e003b49,
0xbdc6bda2,0x3de7bd5b,0xbdd8bd89,0xbc7b3dfe,0x3dfbbcc8,0xbd98bdce,0xbd383def,0x3dffbc17,0xbd44bded,0xbdac3dbe,0x3dfc3caf,0xbd09bdf7,0xbdd53d8e,0x3ddc3d84,0xbb49be00,0xbde53d66,
0xbd71bde2,0x3df8bcf9,0xbdcabd9d,0xbd4f3dea,0x3dd53d8e,0x3d2cbdf1,0xbdf33d21,0x3d893dd8,0x3dedbd44,0xbd98bdce,0xbd093df7,0x3e003b49,0x3cc8bdfb,0xbe003bc9,0x3da73dc2,0x3d93bdd1,
0xbc49bdff,0x3e00bbc9,0xbdb9bdb1,0xbda73dc2,0x3cc83dfb,0x3df8bcf9,0xbdd8bd89,0xbd7c3ddf,0x3d443ded,0x3de7bd5b,0xbdefbd38,0xbd213df3,0x3d8e3dd5,0x3dcebd98,0xbdfcbcaf,0xbc7b3dfe,
0x3d15bdf5,0x3dfd3c96,0xbda7bdc2,0xbdd83d89,0xbd8e3dd5,0x3dbe3dac,0xbc7bbdfe,0xbe00bb49,0xbded3d44,0x3cf93df8,0x3d66bde5,0xbdd1bd93,0xbdfbbcc8,0xbd2c3df1,0x3ddfbd7c,0xbd38bdef,
0x3da2bdc6,0x3df13d2c,0xbd93bdd1,0xbdf73d09,0xbdfb3cc8,0xbc963dfd,0x3db1bdb9,0xbd66bde5,0xbd44bded,0xbe003bc9,0x3dd83d89,0x3dcabd9d,0x3dd5bd8e,0xbcf9bdf8,0xbd383def,0x3dc23da7,
0x3de2bd71,0x3ddc3d84,0xbd7cbddf,0xbe00bb49,0xbdd5bd8e,0xbde73d5b,0x3dff3c17,0x3d93bdd1,0x3dedbd44,0x3c96bdfd,0xbd9d3dca,0x3d383def,0xbcc83dfb,0x3dbe3dac,0xbd21bdf3,0xbdfabce0,
0x3dffbc49,0x3dbe3dac,0xbd4fbdea,0xbdf3bd21,0xbcc8bdfb,0xbddcbd84,0x3d933dd1,0x3dfe3c7b,0x3d443ded,0x3df13d2c,0xbdb9bdb1,0xbdff3c17,0xbd8ebdd5,0xbdfdbc96,0x3dd83d89,0x3df7bd09,
0x3df53d15,0x3d983dce,0xbd21bdf3,0xbdd1bd93,0x3d8ebdd5,0xbbc9be00,0xbd093df7,0x3d383def,0xbded3d44,0xbd843ddc,0x3dc2bda7,0x3ce0bdfa,0x3dfb3cc8,0x3de7bd5b,0xbdfe3c7b,0xbdb93db1,
0x3dc63da2,0x3d5b3de7,0xbce0bdfa,0xbd9dbdca,0x3dfbbcc8,0x3dcebd98,0xbdea3d4f,0xbda73dc2,0xbd44bded,0xbdbebdac,0x3d933dd1,0x3ddf3d7c,0xbdd53d8e,0xbd843ddc,0x3db1bdb9,0x3d21bdf3,
0x3d713de2,0x3cf93df8,0xbc7bbdfe,0xbd38bdef,0x3dd53d8e,0x3df13d2c,0xbde5bd66,0xbdfabce0,0x3dedbd44,0x3dcebd98,0xbddf3d7c,0xbdb93db1,0x3cc8bdfb,0xbbc9be00,0xbc173dff,0x3caf3dfc,
0x3c493dff,0x3bc93e00,0xbb49be00,0xbc17bdff,0x3cc83dfb,0x3cf93df8,0xbce0bdfa,0xbd09bdf7,0x3d443ded,0x3d5b3de7,0xbd4fbdea,0xbd66bde5,0x3d8e3dd5,0x3d983dce,0xbd93bdd1,0xbd9dbdca,
0xbdb53d80,0xbd98bdce,0xbda7bdc2,0xbd89bdd8,0xbdc63da2,0xbbc9be00,0xbc7bbdfe,0x3b49be00,0xbdff3c49,0x3d84bddc,0x3d66bde5,0x3d93bdd1,0xbde2bd71,0x3de7bd5b,0x3ddfbd7c,0x3defbd38,
0x3db53d80,0x3d5b3de7,0x3d933dd1,0x3d093df7,0xbde2bd71,0xbdce3d98,0xbdb13db9,0xbde53d66,0x3d15bdf5,0xbdbebdac,0xbdd8bd89,0xbd9dbdca,0x3dff3c49,0x3d84bddc,0x3d38bdef,0x3da7bdc2,
0xbdb53d80,0xbcf9bdf8,0xbd7cbddf,0x3b49be00,0x3c49bdff,0x3df13d2c,0x3dff3c17,0x3dd13d93,0x3dc63da2,0xbdce3d98,0xbd9d3dca,0xbdef3d38,0xbdf53d15,0xbbc9be00,0xbd21bdf3,0x3ce0bdfa,
0x3db53d80,0x3bc93e00,0x3d4f3dea,0xbd213df3,0x3df5bd15,0xbcf9bdf8,0xbd93bdd1,0x3c7bbdfe,0xbde23d71,0x3d5b3de7,0x3db93db1,0x3c173dff,0x3dc6bda2,0xbd98bdce,0xbdd8bd89,0xbd09bdf7,
0xbdb53d80,0x3c96bdfd,0xbd21bdf3,0x3d93bdd1,0x3da23dc6,0xbdac3dbe,0xbd093df7,0xbdef3d38,0xbc49bdff,0x3df8bcf9,0x3dc2bda7,0x3dfa3ce0,0xbd713de2,0xbdf1bd2c,0xbdfe3c7b,0xbdb1bdb9,
0x3db53d80,0xbd2c3df1,0x3ce03dfa,0xbdca3d9d,0xbd713de2,0x3dfd3c96,0x3deabd4f,0x3dc23da7,0x3df53d15,0xbbc9be00,0xbd93bdd1,0x3d7cbddf,0x3c49bdff,0xbdf83cf9,0xbdb13db9,0xbdf3bd21,
0xbdb53d80,0x3d84bddc,0xbc7bbdfe,0x3defbd38,0xbdffbc49,0xbd5bbde7,0xbde5bd66,0x3ce0bdfa,0xbda23dc6,0xbdfdbc96,0xbddf3d7c,0xbdb1bdb9,0x3d153df5,0xbdac3dbe,0xbc173dff,0xbdfc3caf,
0x3db53d80,0xbdac3dbe,0x3b493e00,0xbdff3c17,0xbd15bdf5,0xbd843ddc,0x3ce03dfa,0xbdf73d09,0xbd71bde2,0xbd2c3df1,0x3d4f3dea,0xbde53d66,0xbda2bdc6,0xbc963dfd,0x3d933dd1,0xbdca3d9d,
0xbdb53d80,0x3dcebd98,0x3c17bdff,0x3dfa3ce0,0x3dc6bda2,0x3e00bbc9,0x3d9dbdca,0x3db13db9,0x3dffbc49,0x3ddc3d84,0x3df3bd21,0x3caf3dfc,0x3de23d71,0x3d5b3de7,0x3df73d09,0xbd4f3dea,
0x3db53d80,0xbde73d5b,0xbcaf3dfc,0xbddfbd7c,0x3de23d71,0xbd98bdce,0xbe003b49,0x3d21bdf3,0xbd153df5,0x3dacbdbe,0xbce0bdfa,0x3dfe3c7b,0xbdffbc49,0x3ddc3d84,0x3deabd4f,0x3c173dff,
0xbdb53d80,0x3df8bcf9,0x3d09bdf7,0x3db13db9,0xbc493dff,0xbd2c3df1,0x3da73dc2,0xbdfc3caf,0xbdc6bda2,0xbd98bdce,0xbdfe3c7b,0x3d4fbdea,0x3df5bd15,0x3e00bbc9,0x3d66bde5,0x3d893dd8,
0x3db53d80,0xbe003bc9,0xbd383def,0xbd66bde5,0xbdf53d15,0x3df8bcf9,0x3cafbdfc,0x3d9d3dca,0x3de2bd71,0xbde73d5b,0x3b493e00,0xbdc2bda7,0xbdc63da2,0x3dcebd98,0xbce0bdfa,0x3ddf3d7c,
0xbdb53d80,0x3dfd3c96,0x3d66bde5,0x3caf3dfc,0xbda2bdc6,0xbdbebdac,0xbddf3d7c,0x3d4fbdea,0x3c493dff,0x3cf93df8,0x3dff3c17,0xbdd83d89,0x3d71bde2,0x3d2cbdf1,0xbdcabd9d,0x3e003b49,
0x3db53d80,0xbdf1bd2c,0xbd893dd8,0x3c7bbdfe,0x3d71bde2,0xbc963dfd,0x3def3d38,0xbdff3c17,0xbdf5bd15,0x3e00bbc9,0x3cafbdfc,0x3d093df7,0xbc493dff,0xbcf9bdf8,0xbe003b49,0x3de5bd66,
0xbdb53d80,0x3ddc3d84,0x3d9dbdca,0xbd4f3dea,0x3dff3c49,0x3de7bd5b,0xbd21bdf3,0x3d893dd8,0x3da2bdc6,0x3c96bdfd,0xbdf7bd09,0x3e003b49,0xbd15bdf5,0xbdbebdac,0xbdc23da7,0x3d93bdd1,
0x3db53d80,0xbdbebdac,0xbdb13db9,0x3da7bdc2,0x3d153df5,0xbddcbd84,0xbd893dd8,0x3d7cbddf,0x3d713de2,0xbdf1bd2c,0xbd383def,0x3d21bdf3,0x3da23dc6,0xbdfdbc96,0xbcaf3dfc,0x3c7bbdfe,
0xbdb53d80,0x3d983dce,0x3dc2bda7,0xbdd83d89,0xbdc63da2,0x3bc93e00,0x3dfebc7b,0xbe00bb49,0xbdff3c49,0xbd843ddc,0x3de53d66,0xbdd1bd93,0xbde2bd71,0xbde73d5b,0x3d7c3ddf,0xbd38bdef,
0x3db53d80,0xbd5bbde7,0xbdd13d93,0x3df7bd09,0xbde2bd71,0x3dcebd98,0xbdb9bdb1,0x3d663de5,0x3d15bdf5,0x3dbe3dac,0x3d89bdd8,0xbdca3d9d,0x3dff3c49,0xbd843ddc,0x3def3d38,0xbdc2bda7,
0xbdb53d80,0x3cf93df8,0x3ddfbd7c,0xbe00bb49,0x3c49bdff,0xbdf1bd2c,0xbc173dff,0x3d93bdd1,0x3dc63da2,0x3dcebd98,0xbdcabd9d,0x3d383def,0xbdf53d15,0x3bc93e00,0x3df3bd21,0xbdfabce0,
0x3db53d80,0xbbc9be00,0xbdea3d4f,0x3df33d21,0x3df5bd15,0x3cf93df8,0x3dd1bd93,0xbdfebc7b,0xbde23d71,0xbd5bbde7,0xbdb13db9,0x3dffbc17,0x3dc6bda2,0x3d983dce,0x3d89bdd8,0xbdf73d09,
0xbdb53d80,0xbc963dfd,0x3df3bd21,0xbdd1bd93,0x3da23dc6,0x3dacbdbe,0xbdf7bd09,0x3d383def,0xbc49bdff,0xbdf83cf9,0x3da73dc2,0x3ce0bdfa,0xbd713de2,0x3df13d2c,0xbc7bbdfe,0xbdb93db1,
0x3db53d80,0x3d2cbdf1,0xbdfa3ce0,0x3d9d3dca,0xbd713de2,0xbdfdbc96,0x3d4f3dea,0x3da7bdc2,0x3df53d15,0x3bc93e00,0x3dd1bd93,0xbddfbd7c,0x3c49bdff,0x3df8bcf9,0xbdb9bdb1,0xbd213df3,
0xbdb53d80,0xbd843ddc,0x3dfebc7b,0xbd38bdef,0xbdffbc49,0x3d5b3de7,0x3d66bde5,0xbdfabce0,0xbda23dc6,0x3dfd3c96,0xbd7cbddf,0xbdb93db1,0x3d153df5,0x3dacbdbe,0xbdffbc17,0x3caf3dfc,
0x3db53d80,0x3dacbdbe,0xbe003b49,0x3c173dff,0xbd15bdf5,0x3d84bddc,0xbdfa3ce0,0x3d093df7,0xbd71bde2,0x3d2cbdf1,0xbdea3d4f,0x3d663de5,0xbda2bdc6,0x3c96bdfd,0xbdd13d93,0x3d9d3dca,
0xbdb53d80,0xbdce3d98,0x3dff3c17,0x3ce0bdfa,0x3dc6bda2,0xbe003bc9,0x3dca3d9d,0x3db9bdb1,0x3dffbc49,0xbddcbd84,0x3d213df3,0x3dfcbcaf,0x3de23d71,0xbd5bbde7,0xbd093df7,0x3dea3d4f,
0x3db53d80,0x3de7bd5b,0xbdfcbcaf,0xbd7c3ddf,0x3de23d71,0x3d983dce,0xbb49be00,0xbdf3bd21,0xbd153df5,0xbdac3dbe,0x3dfabce0,0x3c7bbdfe,0xbdffbc49,0xbddcbd84,0x3d4f3dea,0x3dffbc17,
0xbdb53d80,0xbdf83cf9,0x3df73d09,0x3db9bdb1,0xbc493dff,0x3d2cbdf1,0xbdc23da7,0x3caf3dfc,0xbdc6bda2,0x3d983dce,0xbc7bbdfe,0xbdeabd4f,0x3df5bd15,0xbe003bc9,0x3de53d66,0x3dd8bd89,
0x3db53d80,0x3e00bbc9,0xbdefbd38,0xbde53d66,0xbdf53d15,0xbdf83cf9,0x3dfc3caf,0x3dcabd9d,0x3de2bd71,0x3de7bd5b,0xbe003b49,0xbda73dc2,0xbdc63da2,0xbdce3d98,0x3dfabce0,0x3d7cbddf,
0xbdb53d80,0xbdfdbc96,0x3de53d66,0x3dfcbcaf,0xbda2bdc6,0x3dbe3dac,0xbd7cbddf,0xbdeabd4f,0x3c493dff,0xbcf9bdf8,0xbc173dff,0x3d893dd8,0x3d71bde2,0xbd2c3df1,0x3d9dbdca,0x3b49be00,
0x3db53d80,0x3df13d2c,0xbdd8bd89,0xbdfebc7b,0x3d71bde2,0x3c96bdfd,0xbd383def,0x3c173dff,0xbdf5bd15,0xbe003bc9,0x3dfc3caf,0x3df7bd09,0xbc493dff,0x3cf93df8,0xbb49be00,0xbd66bde5,
0xbdb53d80,0xbddcbd84,0x3dca3d9d,0x3dea3d4f,0x3dff3c49,0xbde73d5b,0x3df3bd21,0x3dd8bd89,0x3da2bdc6,0xbc963dfd,0x3d09bdf7,0x3b49be00,0xbd15bdf5,0x3dbe3dac,0xbda7bdc2,0xbdd1bd93,
0x3db53d80,0x3dbe3dac,0xbdb9bdb1,0xbdc2bda7,0x3d153df5,0x3ddc3d84,0xbdd8bd89,0xbddfbd7c,0x3d713de2,0x3df13d2c,0xbdefbd38,0xbdf3bd21,0x3da23dc6,0x3dfd3c96,0xbdfcbcaf,0xbdfebc7b,
0x3f800000,0x0,0x3f800000,0x0,0x3f800000,0x0,0x3f800000,0x0,0x3f800000,0x0,0x3f800000,0x0,0x3f800000,0x0,0x3f800000,0x0,
0x3f800000,0x0,0x3f7ffb11,0xbc490e90,0x3f7fec43,0xbcc90ab0,0x3f7fd397,0xbd16c32c,0x3f7fb10f,0xbd48fb30,0x3f7f84ab,0xbd7b2b74,0x3f7f4e6d,0xbd96a905,0x3f7f0e58,0xbdafb680,
0x3f800000,0x0,0x3f7fec43,0xbcc90ab0,0x3f7fb10f,0xbd48fb30,0x3f7f4e6d,0xbd96a905,0x3f7ec46d,0xbdc8bd36,0x3f7e1324,0xbdfab273,0x3f7d3aac,0xbe164083,0x3f7c3b28,0xbe2f10a2,
0x3f800000,0x0,0x3f7fd397,0xbd16c32c,0x3f7f4e6d,0xbd96a905,0x3f7e70b0,0xbde1bc2e,0x3f7d3aac,0xbe164083,0x3f7baccd,0xbe3b6ecf,0x3f79c79d,0xbe605c13,0x3f778bc5,0xbe827dc0,
0x3f800000,0x0,0x3f7fb10f,0xbd48fb30,0x3f7ec46d,0xbdc8bd36,0x3f7d3aac,0xbe164083,0x3f7b14be,0xbe47c5c2,0x3f7853f8,0xbe78cfcc,0x3f74fa0b,0xbe94a031,0x3f710908,0xbeac7cd4,
0x3f800000,0x0,0x3f7f84ab,0xbd7b2b74,0x3f7e1324,0xbdfab273,0x3f7baccd,0xbe3b6ecf,0x3f7853f8,0xbe78cfcc,0x3f740bdd,0xbe9aa086,0x3f6ed89e,0xbeb8442a,0x3f68bf3c,0xbed53641,
0x3f800000,0x0,0x3f7f4e6d,0xbd96a905,0x3f7d3aac,0xbe164083,0x3f79c79d,0xbe605c13,0x3f74fa0b,0xbe94a031,0x3f6ed89e,0xbeb8442a,0x3f676bd8,0xbedae880,0x3f5ebe05,0xbefc5d27,
0x3f800000,0x0,0x3f7f0e58,0xbdafb680,0x3f7c3b28,0xbe2f10a2,0x3f778bc5,0xbe827dc0,0x3f710908,0xbeac7cd4,0x3f68bf3c,0xbed53641,0x3f5ebe05,0xbefc5d27,0x3f531849,0xbf10d3cd,
0x3f800000,0x0,0x3f7b14be,0xbe47c5c2,0x3f6c835e,0xbec3ef15,0x3f54db31,0xbf0e39da,0x3f3504f3,0xbf3504f3,0x3f0e39da,0xbf54db31,0x3ec3ef15,0xbf6c835e,0x3e47c5c2,0xbf7b14be,
0x3f800000,0x0,0x3f7a7302,0xbe541501,0x3f6a09a7,0xbecf7bca,0x3f4f7a1f,0xbf15f6d9,0x3f2beb4a,0xbf3daef9,0x3f00e7e4,0xbf5d2d53,0x3ea09ae5,0xbf731447,0x3de1bc2e,0xbf7e70b0,
0x3f800000,0x0,0x3f79c79d,0xbe605c13,0x3f676bd8,0xbedae880,0x3f49d112,0xbf1d7fd1,0x3f226799,0xbf45e403,0x3ee63375,0xbf64aa59,0x3e78cfcc,0xbf7853f8,0x3cc90ab0,0xbf7fec43,
0x3f800000,0x0,0x3f791298,0xbe6c9a7f,0x3f64aa59,0xbee63375,0x3f43e200,0xbf24d225,0x3f187fc0,0xbf4d9f02,0x3ec9b953,0xbf6b4b0c,0x3e2f10a2,0xbf7c3b28,0xbd7b2b74,0xbf7f84ab,
0x3f800000,0x0,0x3f7853f8,0xbe78cfcc,0x3f61c598,0xbef15aea,0x3f3daef9,0xbf2beb4a,0x3f0e39da,0xbf54db31,0x3eac7cd4,0xbf710908,0x3dc8bd36,0xbf7ec46d,0xbe164083,0xbf7d3aac,
0x3f800000,0x0,0x3f778bc5,0xbe827dc0,0x3f5ebe05,0xbefc5d27,0x3f373a23,0xbf32c8c9,0x3f039c3d,0xbf5b941a,0x3e8e9a22,0xbf75dec6,0x3cc90ab0,0xbf7fec43,0xbe6c9a7f,0xbf791298,
0x3f800000,0x0,0x3f76ba07,0xbe888e93,0x3f5b941a,0xbf039c3d,0x3f3085bb,0xbf396842,0x3ef15aea,0xbf61c598,0x3e605c13,0xbf79c79d,0xbd48fb30,0xbf7fb10f,0xbea09ae5,0xbf731447,
0x3f800000,0x0,0x3f75dec6,0xbe8e9a22,0x3f584853,0xbf08f59b,0x3f299415,0xbf3fc767,0x3edae880,0xbf676bd8,0x3e22abb6,0xbf7cbfc9,0xbdfab273,0xbf7e1324,0xbec9b953,0xbf6b4b0c,
0x3f800000,0x0,0x3f7ec46d,0xbdc8bd36,0x3f7b14be,0xbe47c5c2,0x3f74fa0b,0xbe94a031,0x3f6c835e,0xbec3ef15,0x3f61c598,0xbef15aea,0x3f54db31,0xbf0e39da,0x3f45e403,0xbf226799,
0x3f800000,0x0,0x3f6b4b0c,0xbec9b953,0x3f3085bb,0xbf396842,0x3eb263ef,0xbf6ff573,0xbd48fb30,0xbf7fb10f,0xbee0924f,0xbf660f88,0xbf41d870,0xbf273656,0xbf740bdd,0xbe9aa086,
0x3f800000,0x0,0x3f6a09a7,0xbecf7bca,0x3f2beb4a,0xbf3daef9,0x3ea09ae5,0xbf731447,0xbdc8bd36,0xbf7ec46d,0xbefc5d27,0xbf5ebe05,0xbf4d9f02,0xbf187fc0,0xbf79c79d,0xbe605c13,
0x3f800000,0x0,0x3f68bf3c,0xbed53641,0x3f273656,0xbf41d870,0x3e8e9a22,0xbf75dec6,0xbe164083,0xbf7d3aac,0xbf0b9a6b,0xbf5695e5,0xbf584853,0xbf08f59b,0xbf7dabcc,0xbe09cf86,
0x3f800000,0x0,0x3f676bd8,0xbedae880,0x3f226799,0xbf45e403,0x3e78cfcc,0xbf7853f8,0xbe47c5c2,0xbf7b14be,0xbf187fc0,0xbf4d9f02,0xbf61c598,0xbef15aea,0xbf7fb10f,0xbd48fb30,
0x3f800000,0x0,0x3f660f88,0xbee0924f,0x3f1d7fd1,0xbf49d112,0x3e541501,0xbf7a7302,0xbe78cfcc,0xbf7853f8,0xbf24d225,0xbf43e200,0xbf6a09a7,0xbecf7bca,0xbf7fd397,0x3d16c32c,
0x3f800000,0x0,0x3f64aa59,0xbee63375,0x3f187fc0,0xbf4d9f02,0x3e2f10a2,0xbf7c3b28,0xbe94a031,0xbf74fa0b,0xbf3085bb,0xbf396842,0xbf710908,0xbeac7cd4,0xbf7e1324,0x3dfab273,
0x3f800000,0x0,0x3f633c5a,0xbeebcbbb,0x3f13682a,0xbf514d3d,0x3e09cf86,0xbf7dabcc,0xbeac7cd4,0xbf710908,0xbf3b8f3b,0xbf2e3bde,0xbf76ba07,0xbe888e93,0xbf7a7302,0x3e541501,
0x3f800000,0x0,0x3f74fa0b,0xbe94a031,0x3f54db31,0xbf0e39da,0x3f226799,0xbf45e403,0x3ec3ef15,0xbf6c835e,0x3dc8bd36,0xbf7ec46d,0xbe47c5c2,0xbf7b14be,0xbef15aea,0xbf61c598,
0x3f800000,0x0,0x3f531849,0xbf10d3cd,0x3eb8442a,0xbf6ed89e,0xbe6c9a7f,0xbf791298,0xbf3daef9,0xbf2beb4a,0xbf7dabcc,0xbe09cf86,0xbf64aa59,0x3ee63375,0xbef6e0cb,0x3f604621,
0x3f800000,0x0,0x3f514d3d,0xbf13682a,0x3eac7cd4,0xbf710908,0xbe888e93,0xbf76ba07,0xbf45e403,0xbf226799,0xbf7f4e6d,0xbd96a905,0xbf5b941a,0x3f039c3d,0xbecf7bca,0x3f6a09a7,
0x3f800000,0x0,0x3f4f7a1f,0xbf15f6d9,0x3ea09ae5,0xbf731447,0xbe9aa086,0xbf740bdd,0xbf4d9f02,0xbf187fc0,0xbf7ffb11,0xbc490e90,0xbf514d3d,0x3f13682a,0xbea68f12,0x3f721352,
0x3f800000,0x0,0x3f4d9f02,0xbf187fc0,0x3e94a031,0xbf74fa0b,0xbeac7cd4,0xbf710908,0xbf54db31,0xbf0e39da,0xbf7fb10f,0x3d48fb30,0xbf45e403,0x3f226799,0xbe78cfcc,0x3f7853f8,
0x3f800000,0x0,0x3f4bbbf8,0xbf1b02c6,0x3e888e93,0xbf76ba07,0xbebe1d4a,0xbf6db293,0xbf5b941a,0xbf039c3d,0xbf7e70b0,0x3de1bc2e,0xbf396842,0x3f3085bb,0xbe22abb6,0x3f7cbfc9,
0x3f800000,0x0,0x3f49d112,0xbf1d7fd1,0x3e78cfcc,0xbf7853f8,0xbecf7bca,0xbf6a09a7,0xbf61c598,0xbef15aea,0xbf7c3b28,0x3e2f10a2,0xbf2beb4a,0x3f3daef9,0xbd96a905,0x3f7f4e6d,
0x3f800000,0x0,0x3f47de65,0xbf1ff6cb,0x3e605c13,0xbf79c79d,0xbee0924f,0xbf660f88,0xbf676bd8,0xbedae880,0xbf791298,0x3e6c9a7f,0xbf1d7fd1,0x3f49d112,0x3c490e90,0x3f7ffb11,
0x3f800000,0x0,0x3f800000,0x0,0x3f800000,0x0,0x3f800000,0x0,0x40000000,0x0,0x3f800000,0x0,0x3f800000,0x0,0x3f800000,0x0,
0x3f800000,0x0,0x3f7ffb11,0xbc490e90,0x3f7fec43,0xbcc90ab0,0x3f7fd397,0xbd16c32c,0x3fffb10f,0xbdc8fb30,0x3f7f84ab,0xbd7b2b74,0x3f7f4e6d,0xbd96a905,0x3f7f0e58,0xbdafb680,
0x3f800000,0x0,0x3f7fec43,0xbcc90ab0,0x3f7fb10f,0xbd48fb30,0x3f7f4e6d,0xbd96a905,0x3ffec46d,0xbe48bd36,0x3f7e1324,0xbdfab273,0x3f7d3aac,0xbe164083,0x3f7c3b28,0xbe2f10a2,
0x3f800000,0x0,0x3f7fd397,0xbd16c32c,0x3f7f4e6d,0xbd96a905,0x3f7e70b0,0xbde1bc2e,0x3ffd3aac,0xbe964083,0x3f7baccd,0xbe3b6ecf,0x3f79c79d,0xbe605c13,0x3f778bc5,0xbe827dc0,
0x3f800000,0x0,0x3f7fb10f,0xbd48fb30,0x3f7ec46d,0xbdc8bd36,0x3f7d3aac,0xbe164083,0x3ffb14be,0xbec7c5c2,0x3f7853f8,0xbe78cfcc,0x3f74fa0b,0xbe94a031,0x3f710908,0xbeac7cd4,
0x3f800000,0x0,0x3f7f84ab,0xbd7b2b74,0x3f7e1324,0xbdfab273,0x3f7baccd,0xbe3b6ecf,0x3ff853f8,0xbef8cfcc,0x3f740bdd,0xbe9aa086,0x3f6ed89e,0xbeb8442a,0x3f68bf3c,0xbed53641,
0x3f800000,0x0,0x3f7f4e6d,0xbd96a905,0x3f7d3aac,0xbe164083,0x3f79c79d,0xbe605c13,0x3ff4fa0b,0xbf14a031,0x3f6ed89e,0xbeb8442a,0x3f676bd8,0xbedae880,0x3f5ebe05,0xbefc5d27,
0x3f800000,0x0,0x3f7f0e58,0xbdafb680,0x3f7c3b28,0xbe2f10a2,0x3f778bc5,0xbe827dc0,0x3ff10908,0xbf2c7cd4,0x3f68bf3c,0xbed53641,0x3f5ebe05,0xbefc5d27,0x3f531849,0xbf10d3cd,
0x3f800000,0x0,0x3f7ec46d,0xbdc8bd36,0x3f7b14be,0xbe47c5c2,0x3f74fa0b,0xbe94a031,0x3fec835e,0xbf43ef15,0x3f61c598,0xbef15aea,0x3f54db31,0xbf0e39da,0x3f45e403,0xbf226799,
0x3f800000,0x0,0x3f7e70b0,0xbde1bc2e,0x3f79c79d,0xbe605c13,0x3f721352,0xbea68f12,0x3fe76bd8,0xbf5ae880,0x3f59f26a,0xbf064b82,0x3f49d112,0xbf1d7fd1,0x3f373a23,0xbf32c8c9,
0x3f800000,0x0,0x3f7e1324,0xbdfab273,0x3f7853f8,0xbe78cfcc,0x3f6ed89e,0xbeb8442a,0x3fe1c598,0xbf715aea,0x3f514d3d,0xbf13682a,0x3f3daef9,0xbf2beb4a,0x3f273656,0xbf41d870,
0x3f800000,0x0,0x3f7dabcc,0xbe09cf86,0x3f76ba07,0xbe888e93,0x3f6b4b0c,0xbec9b953,0x3fdb941a,0xbf839c3d,0x3f47de65,0xbf1ff6cb,0x3f3085bb,0xbf396842,0x3f15f6d9,0xbf4f7a1f,
0x3f800000,0x0,0x3f7d3aac,0xbe164083,0x3f74fa0b,0xbe94a031,0x3f676bd8,0xbedae880,0x3fd4db31,0xbf8e39da,0x3f3daef9,0xbf2beb4a,0x3f226799,0xbf45e403,0x3f039c3d,0xbf5b941a,
0x3f800000,0x0,0x3f7cbfc9,0xbe22abb6,0x3f731447,0xbea09ae5,0x3f633c5a,0xbeebcbbb,0x3fcd9f02,0xbf987fc0,0x3f32c8c9,0xbf373a23,0x3f13682a,0xbf514d3d,0x3ee0924f,0xbf660f88,
0x3f800000,0x0,0x3f7c3b28,0xbe2f10a2,0x3f710908,0xbeac7cd4,0x3f5ebe05,0xbefc5d27,0x3fc5e403,0xbfa26799,0x3f273656,0xbf41d870,0x3f039c3d,0xbf5b941a,0x3eb8442a,0xbf6ed89e,
0x3f800000,0x0,0x3f7baccd,0xbe3b6ecf,0x3f6ed89e,0xbeb8442a,0x3f59f26a,0xbf064b82,0x3fbdaef9,0xbfabeb4a,0x3f1b02c6,0xbf4bbbf8,0x3ee63375,0xbf64aa59,0x3e8e9a22,0xbf75dec6,
0x3f800000,0x0,0x3f7b14be,0xbe47c5c2,0x3f6c835e,0xbec3ef15,0x3f54db31,0xbf0e39da,0x3fb504f3,0xbfb504f3,0x3f0e39da,0xbf54db31,0x3ec3ef15,0xbf6c835e,0x3e47c5c2,0xbf7b14be,
0x3f800000,0x0,0x3f7a7302,0xbe541501,0x3f6a09a7,0xbecf7bca,0x3f4f7a1f,0xbf15f6d9,0x3fabeb4a,0xbfbdaef9,0x3f00e7e4,0xbf5d2d53,0x3ea09ae5,0xbf731447,0x3de1bc2e,0xbf7e70b0,
0x3f800000,0x0,0x3f79c79d,0xbe605c13,0x3f676bd8,0xbedae880,0x3f49d112,0xbf1d7fd1,0x3fa26799,0xbfc5e403,0x3ee63375,0xbf64aa59,0x3e78cfcc,0xbf7853f8,0x3cc90ab0,0xbf7fec43,
0x3f800000,0x0,0x3f791298,0xbe6c9a7f,0x3f64aa59,0xbee63375,0x3f43e200,0xbf24d225,0x3f987fc0,0xbfcd9f02,0x3ec9b953,0xbf6b4b0c,0x3e2f10a2,0xbf7c3b28,0xbd7b2b74,0xbf7f84ab,
0x3f800000,0x0,0x3f7853f8,0xbe78cfcc,0x3f61c598,0xbef15aea,0x3f3daef9,0xbf2beb4a,0x3f8e39da,0xbfd4db31,0x3eac7cd4,0xbf710908,0x3dc8bd36,0xbf7ec46d,0xbe164083,0xbf7d3aac,
0x3f800000,0x0,0x3f778bc5,0xbe827dc0,0x3f5ebe05,0xbefc5d27,0x3f373a23,0xbf32c8c9,0x3f839c3d,0xbfdb941a,0x3e8e9a22,0xbf75dec6,0x3cc90ab0,0xbf7fec43,0xbe6c9a7f,0xbf791298,
0x3f800000,0x0,0x3f76ba07,0xbe888e93,0x3f5b941a,0xbf039c3d,0x3f3085bb,0xbf396842,0x3f715aea,0xbfe1c598,0x3e605c13,0xbf79c79d,0xbd48fb30,0xbf7fb10f,0xbea09ae5,0xbf731447,
0x3f800000,0x0,0x3f75dec6,0xbe8e9a22,0x3f584853,0xbf08f59b,0x3f299415,0xbf3fc767,0x3f5ae880,0xbfe76bd8,0x3e22abb6,0xbf7cbfc9,0xbdfab273,0xbf7e1324,0xbec9b953,0xbf6b4b0c,
0x3f800000,0x0,0x3f74fa0b,0xbe94a031,0x3f54db31,0xbf0e39da,0x3f226799,0xbf45e403,0x3f43ef15,0xbfec835e,0x3dc8bd36,0xbf7ec46d,0xbe47c5c2,0xbf7b14be,0xbef15aea,0xbf61c598,
0x3f800000,0x0,0x3f740bdd,0xbe9aa086,0x3f514d3d,0xbf13682a,0x3f1b02c6,0xbf4bbbf8,0x3f2c7cd4,0xbff10908,0x3d16c32c,0xbf7fd397,0xbe888e93,0xbf76ba07,0xbf0b9a6b,0xbf5695e5,
0x3f800000,0x0,0x3f731447,0xbea09ae5,0x3f4d9f02,0xbf187fc0,0x3f13682a,0xbf514d3d,0x3f14a031,0xbff4fa0b,0xbcc90ab0,0xbf7fec43,0xbeac7cd4,0xbf710908,0xbf1d7fd1,0xbf49d112,
0x3f800000,0x0,0x3f721352,0xbea68f12,0x3f49d112,0xbf1d7fd1,0x3f0b9a6b,0xbf5695e5,0x3ef8cfcc,0xbff853f8,0xbdafb680,0xbf7f0e58,0xbecf7bca,0xbf6a09a7,0xbf2e3bde,0xbf3b8f3b,
0x3f800000,0x0,0x3f710908,0xbeac7cd4,0x3f45e403,0xbf226799,0x3f039c3d,0xbf5b941a,0x3ec7c5c2,0xbffb14be,0xbe164083,0xbf7d3aac,0xbef15aea,0xbf61c598,0xbf3daef9,0xbf2beb4a,
0x3f800000,0x0,0x3f6ff573,0xbeb263ef,0x3f41d870,0xbf273656,0x3ef6e0cb,0xbf604621,0x3e964083,0xbffd3aac,0xbe541501,0xbf7a7302,0xbf08f59b,0xbf584853,0xbf4bbbf8,0xbf1b02c6,
0x3f800000,0x0,0x3f6ed89e,0xbeb8442a,0x3f3daef9,0xbf2beb4a,0x3ee63375,0xbf64aa59,0x3e48bd36,0xbffec46d,0xbe888e93,0xbf76ba07,0xbf187fc0,0xbf4d9f02,0xbf584853,0xbf08f59b,
0x3f800000,0x0,0x3f6db293,0xbebe1d4a,0x3f396842,0xbf3085bb,0x3ed53641,0xbf68bf3c,0x3dc8fb30,0xbfffb10f,0xbea68f12,0xbf721352,0xbf273656,0xbf41d870,0xbf633c5a,0xbeebcbbb,
0x3f800000,0x0,0x3f7fffb1,0xbb490fc6,0x3f7ffec4,0xbbc90f88,0x3f7ffd39,0xbc16cb58,0x3ffffb11,0xbcc90e90,0x3f7ff84a,0xbc7b514b,0x3f7ff4e6,0xbc96c9b6,0x3f7ff0e3,0xbcafea69,
0x3f800000,0x0,0x3f7ff84a,0xbc7b514b,0x3f7fe129,0xbcfb49ba,0x3f7fba9e,0xbd3c6dd5,0x3fff84ab,0xbdfb2b74,0x3f7f3f54,0xbd9cecf9,0x3f7eea9d,0xbdbc3ac3,0x3f7e868b,0xbddb7d37,
0x3f800000,0x0,0x3f7fe705,0xbce22a7a,0x3f7f9c18,0xbd621469,0x3f7f1f49,0xbda973ba,0x3ffe70b0,0xbe61bc2e,0x3f7d906e,0xbe0cec4a,0x3f7c7eb0,0xbe28defc,0x3f7b3bab,0xbe44b0b9,
0x3f800000,0x0,0x3f7fcbe2,0xbd2351cb,0x3f7f2f9d,0xbda3308c,0x3f7e2b72,0xbdf475c0,0x3ffcbfc9,0xbea2abb6,0x3f7aed37,0xbe4ada4f,0x3f78b47b,0xbe72b651,0x3f76167a,0xbe8d17c0,
0x3f800000,0x0,0x3f7fa6e3,0xbd55880e,0x3f7e9bc9,0xbdd53db9,0x3f7cdf6c,0xbe1f917b,0x3ffa7302,0xbed41501,0x3f77583a,0xbe840270,0x3f73913f,0xbe9d9e78,0x3f6f20b0,0xbeb6ccc3,
0x3f800000,0x0,0x3f7f7808,0xbd83db0a,0x3f7de0b1,0xbe039502,0x3f7b3bab,0xbe44b0b9,0x3ff78bc5,0xbf027dc0,0x3f72d4eb,0xbea21887,0x3f6d1c1d,0xbec1071e,0x3f666771,0xbedf28a9,
0x3f800000,0x0,0x3f7f3f54,0xbd9cecf9,0x3f7cfe73,0xbe1c76de,0x3f7940c0,0xbe698bba,0x3ff40bdd,0xbf1aa086,0x3f6d67a1,0xbebf926f,0x3f655e0b,0xbee363fa,0x3f5bfb34,0xbf02ef9f,
0x3f800000,0x0,0x3f7efcc9,0xbdb5f8da,0x3f7bf531,0xbe354098,0x3f76ef5b,0xbe870ada,0x3feff573,0xbf3263ef,0x3f671599,0xbedc53c1,0x3f5c61c7,0xbf0242b1,0x3f4fefa8,0xbf1553b7,
0x3f800000,0x0,0x3f7eb069,0xbdcefdb7,0x3f7ac516,0xbe4dee60,0x3f74484b,0xbe9920fe,0x3feb4b0c,0xbf49b953,0x3f5fe4e9,0xbef840c8,0x3f5233c6,0xbf121eb0,0x3f425b89,0xbf269de3,
0x3f800000,0x0,0x3f7e5a38,0xbde7fa9a,0x3f796e4e,0xbe667c66,0x3f714c7a,0xbeab0201,0x3fe60f88,0xbf60924f,0x3f57dc7f,0xbf099f4e,0x3f46e22a,0xbf212ff9,0x3f33587a,0xbf36ad7f,
0x3f800000,0x0,0x3f7dfa38,0xbe007745,0x3f77f110,0xbe7ee6e1,0x3f6dfcf2,0xbebca7af,0x3fe04621,0xbf76e0cb,0x3f4f0417,0xbf16999f,0x3f3a7ca4,0xbf2f61a5,0x3f2302d3,0xbf456439,
0x3f800000,0x0,0x3f7d906e,0xbe0cec4a,0x3f764d97,0xbe8b9507,0x3f6a5ad9,0xbece0bea,0x3fd9f26a,0xbf864b82,0x3f456439,0xbf2302d3,0x3f2d1469,0xbf3ca003,0x3f11796b,0xbf52a649,
0x3f800000,0x0,0x3f7d1cdd,0xbe195be0,0x3f748422,0xbe97a117,0x3f666771,0xbedf28a9,0x3fd31849,0xbf90d3cd,0x3f3b0629,0xbf2ecef7,0x3f1ebc12,0xbf48d8b3,0x3efdbabb,0xbf5e5aa6,
0x3f800000,0x0,0x3f7c9f8a,0xbe25c58c,0x3f7294f8,0xbea395c5,0x3f62241a,0xbeeff7fb,0x3fcbbbf8,0xbf9b02c6,0x3f2ff3e6,0xbf39f2ac,0x3f0f8784,0xbf53fac3,0x3ed6a399,0xbf686b39,
0x3f800000,0x0,0x3f7c187a,0xbe3228d4,0x3f708066,0xbeaf713a,0x3f5d924d,0xbf003a06,0x3fc3e200,0xbfa4d225,0x3f24381a,0xbf446337,0x3eff17b2,0xbf5df6be,0x3eadf73c,0xbf70c501,
0x3f800000,0x0,0x3f7b87b2,0xbe3e853e,0x3f6e46be,0xbebb31a0,0x3f58b3a1,0xbf084b92,0x3fbb8f3b,0xbfae3bde,0x3f17de12,0xbf4e1689,0x3eddbe79,0xbf66becc,0x3e840270,0xbf77583a,
0x3f800000,0x0,0x3f7aed37,0xbe4ada4f,0x3f6be858,0xbec6d529,0x3f5389c7,0xbf102dd5,0x3fb2c8c9,0xbfb73a23,0x3f0af1b7,0xbf570348,0x3ebb31a0,0xbf6e46be,0x3e3228d4,0xbf7c187a,
0x3f800000,0x0,0x3f7a4910,0xbe57278f,0x3f696591,0xbed25a09,0x3f4e1689,0xbf17de12,0x3fa99415,0xbfbfc767,0x3efafef7,0xbf5f20db,0x3e97a117,0xbf748422,0x3db5f8da,0xbf7efcc9,
0x3f800000,0x0,0x3f799b43,0xbe636c83,0x3f66becc,0xbeddbe79,0x3f485bca,0xbf1f599f,0x3f9ff6cb,0xbfc7de65,0x3edf28a9,0xbf666771,0x3e667c66,0xbf796e4e,0x3b490fc6,0xbf7fffb1,
0x3f800000,0x0,0x3f78e3d6,0xbe6fa8b2,0x3f63f473,0xbee900b7,0x3f425b89,0xbf269de3,0x3f95f6d9,0xbfcf7a1f,0x3ec27b55,0xbf6cd007,0x3e1c76de,0xbf7cfe73,0xbda973ba,0xbf7f1f49,
0x3f800000,0x0,0x3f7822d1,0xbe7bdba4,0x3f6106f2,0xbef41f07,0x3f3c17d9,0xbf2da859,0x3f8b9a6b,0xbfd695e5,0x3ea5129f,0xbf725470,0x3da3308c,0xbf7f2f9d,0xbe2bf804,0xbf7c5d3a,
0x3f800000,0x0,0x3f77583a,0xbe840270,0x3f5df6be,0xbeff17b2,0x3f3592e7,0xbf34768f,0x3f80e7e4,0xbfdd2d53,0x3e870ada,0xbf76ef5b,0x3bc90f88,0xbf7ffec4,0xbe80f8c0,0xbf77beb7,
0x3f800000,0x0,0x3f76841b,0xbe8a11f7,0x3f5ac450,0xbf04f484,0x3f2ecef7,0xbf3b0629,0x3f6bcbbb,0xbfe33c5a,0x3e5101f1,0xbf7a9c59,0xbd8a200a,0xbf7f6ac7,0xbeab0201,0xbf714c7a,
0x3f800000,0x0,0x3f75a67b,0xbe901c2c,0x3f577026,0xbf0a48ad,0x3f27ce61,0xbf4154e1,0x3f553641,0xbfe8bf3c,0x3e1324ca,0xbf7d57de,0xbe1008b7,0xbf7d7474,0xbed3c867,0xbf6912ae,
0x3f800000,0x0,0x3f74bf62,0xbe9620d2,0x3f53fac3,0xbf0f8784,0x3f209393,0xbf476085,0x3f3e1d4a,0xbfedb293,0x3da973ba,0xbf7f1f49,0xbe5a3997,0xbf7a1e84,0xbefafef7,0xbf5f20db,
0x3f800000,0x0,0x3f73ced9,0xbe9c1faf,0x3f5064af,0xbf14b039,0x3f19210f,0xbf4d26fd,0x3f268f12,0xbff21352,0x3cafea69,0xbf7ff0e3,0xbe919ddd,0xbf756d97,0xbf102dd5,0xbf5389c7,
0x3f800000,0x0,0x3f72d4eb,0xbea21887,0x3f4cae79,0xbf19c200,0x3f11796b,0xbf52a649,0x3f0e9a22,0xbff5dec6,0xbd2351cb,0xbf7fcbe2,0xbeb554ec,0xbf6f6830,0xbf21cbfb,0xbf466354,
0x3f800000,0x0,0x3f71d19f,0xbea80b1f,0x3f48d8b3,0xbf1ebc12,0x3f099f4e,0xbf57dc7f,0x3eec9a7f,0xbff91298,0xbdcefdb7,0xbf7eb069,0xbed8106b,0xbf6816a8,0xbf3238aa,0xbf37c655,
0x3f800000,0x0,0x3f70c501,0xbeadf73c,0x3f44e3f5,0xbf239da9,0x3f019573,0xbf5cc7d1,0x3ebb6ecf,0xbffbaccd,0xbe25c58c,0xbf7c9f8a,0xbef9a02d,0xbf5f8327,0xbf4154e1,0xbf27ce61,
0x3f800000,0x0,0x3f6faf1b,0xbeb3dca5,0x3f40d0da,0xbf286605,0x3ef2bd43,0xbf61668a,0x3e89cf86,0xbffdabcc,0xbe636c83,0xbf799b43,0xbf0cead0,0xbf55b993,0xbf4f0417,0xbf16999f,
0x3f800000,0x0,0x3f6e8ff8,0xbeb9bb1e,0x3f3ca003,0xbf2d1469,0x3ee1fb6a,0xbf65b710,0x3e2fb680,0xbfff0e58,0xbe901c2c,0xbf75a67b,0xbf1c420c,0xbf4ac77f,0xbf5b2c79,0xbf044889,
0x3f800000,0x0,0x3f6d67a1,0xbebf926f,0x3f385216,0xbf31a81d,0x3ed0eb2a,0xbf69b7e4,0x3d96c32c,0xbfffd397,0xbeadf73c,0xbf70c501,0xbf2ac082,0xbf3ebc1b,0xbf65b710,0xbee1fb6a,
0x3f800000,0x0,0x3f7ffec4,0xbbc90f88,0x3f7ffb11,0xbc490e90,0x3f7ff4e6,0xbc96c9b6,0x3fffec43,0xbd490ab0,0x3f7fe129,0xbcfb49ba,0x3f7fd397,0xbd16c32c,0x3f7fc38f,0xbd2fe007,
0x3f800000,0x0,0x3f7ff4e6,0xbc96c9b6,0x3f7fd397,0xbd16c32c,0x3f7f9c18,0xbd621469,0x3fff4e6d,0xbe16a905,0x3f7eea9d,0xbdbc3ac3,0x3f7e70b0,0xbde1bc2e,0x3f7de0b1,0xbe039502,
0x3f800000,0x0,0x3f7fe129,0xbcfb49ba,0x3f7f84ab,0xbd7b2b74,0x3f7eea9d,0xbdbc3ac3,0x3ffe1324,0xbe7ab273,0x3f7cfe73,0xbe1c76de,0x3f7baccd,0xbe3b6ecf,0x3f7a1e84,0xbe5a3997,
0x3f800000,0x0,0x3f7fc38f,0xbd2fe007,0x3f7f0e58,0xbdafb680,0x3f7de0b1,0xbe039502,0x3ffc3b28,0xbeaf10a2,0x3f7a1e84,0xbe5a3997,0x3f778bc5,0xbe827dc0,0x3f748422,0xbe97a117,
0x3f800000,0x0,0x3f7f9c18,0xbd621469,0x3f7e70b0,0xbde1bc2e,0x3f7c7eb0,0xbe28defc,0x3ff9c79d,0xbee05c13,0x3f764d97,0xbe8b9507,0x3f721352,0xbea68f12,0x3f6d1c1d,0xbec1071e,
0x3f800000,0x0,0x3f7f6ac7,0xbd8a200a,0x3f7dabcc,0xbe09cf86,0x3f7ac516,0xbe4dee60,0x3ff6ba07,0xbf088e93,0x3f718f57,0xbea986c4,0x3f6b4b0c,0xbec9b953,0x3f63f473,0xbee900b7,
0x3f800000,0x0,0x3f7f2f9d,0xbda3308c,0x3f7cbfc9,0xbe22abb6,0x3f78b47b,0xbe72b651,0x3ff31447,0xbf209ae5,0x3f6be858,0xbec6d529,0x3f633c5a,0xbeebcbbb,0x3f591e6a,0xbf07a136,
0x3f800000,0x0,0x3f7eea9d,0xbdbc3ac3,0x3f7baccd,0xbe3b6ecf,0x3f764d97,0xbe8b9507,0x3feed89e,0xbf38442a,0x3f655e0b,0xbee363fa,0x3f59f26a,0xbf064b82,0x3f4cae79,0xbf19c200,
0x3f800000,0x0,0x3f7e9bc9,0xbdd53db9,0x3f7a7302,0xbe541501,0x3f73913f,0xbe9d9e78,0x3fea09a7,0xbf4f7bca,0x3f5df6be,0xbeff17b2,0x3f4f7a1f,0xbf15f6d9,0x3f3ebc1b,0xbf2ac082,
0x3f800000,0x0,0x3f7e4323,0xbdee3876,0x3f791298,0xbe6c9a7f,0x3f708066,0xbeaf713a,0x3fe4aa59,0xbf663375,0x3f55b993,0xbf0cead0,0x3f43e200,0xbf24d225,0x3f2f61a5,0xbf3a7ca4,
0x3f800000,0x0,0x3f7de0b1,0xbe039502,0x3f778bc5,0xbe827dc0,0x3f6d1c1d,0xbec1071e,0x3fdebe05,0xbf7c5d27,0x3f4cae79,0xbf19c200,0x3f373a23,0xbf32c8c9,0x3f1ebc12,0xbf48d8b3,
0x3f800000,0x0,0x3f7d7474,0xbe1008b7,0x3f75dec6,0xbe8e9a22,0x3f696591,0xbed25a09,0x3fd84853,0xbf88f59b,0x3f42de29,0xbf26050a,0x3f299415,0xbf3fc767,0x3f0cead0,0xbf55b993,
0x3f800000,0x0,0x3f7cfe73,0xbe1c76de,0x3f740bdd,0xbe9aa086,0x3f655e0b,0xbee363fa,0x3fd14d3d,0xbf93682a,0x3f385216,0xbf31a81d,0x3f1b02c6,0xbf4bbbf8,0x3ef41f07,0xbf6106f2,
0x3f800000,0x0,0x3f7c7eb0,0xbe28defc,0x3f721352,0xbea68f12,0x3f6106f2,0xbef41f07,0x3fc9d112,0xbf9d7fd1,0x3f2d1469,0xbf3ca003,0x3f0b9a6b,0xbf5695e5,0x3ecc9b8b,0xbf6aab7b,
0x3f800000,0x0,0x3f7bf531,0xbe354098,0x3f6ff573,0xbeb263ef,0x3f5c61c7,0xbf0242b1,0x3fc1d870,0xbfa73656,0x3f212ff9,0xbf46e22a,0x3ef6e0cb,0xbf604621,0x3ea395c5,0xbf7294f8,
0x3f800000,0x0,0x3f7b61fc,0xbe419b37,0x3f6db293,0xbebe1d4a,0x3f577026,0xbf0a48ad,0x3fb96842,0xbfb085bb,0x3f14b039,0xbf5064af,0x3ed53641,0xbf68bf3c,0x3e72b651,0xbf78b47b,
0x3f800000,0x0,0x3f7ac516,0xbe4dee60,0x3f6b4b0c,0xbec9b953,0x3f5233c6,0xbf121eb0,0x3fb085bb,0xbfb96842,0x3f07a136,0xbf591e6a,0x3eb263ef,0xbf6ff573,0x3e1c76de,0xbf7cfe73,
0x3f800000,0x0,0x3f7a1e84,0xbe5a3997,0x3f68bf3c,0xbed53641,0x3f4cae79,0xbf19c200,0x3fa73656,0xbfc1d870,0x3ef41f07,0xbf6106f2,0x3e8e9a22,0xbf75dec6,0x3d8a200a,0xbf7f6ac7,
0x3f800000,0x0,0x3f796e4e,0xbe667c66,0x3f660f88,0xbee0924f,0x3f46e22a,0xbf212ff9,0x3f9d7fd1,0xbfc9d112,0x3ed8106b,0xbf6816a8,0x3e541501,0xbf7a7302,0xbc96c9b6,0xbf7ff4e6,
0x3f800000,0x0,0x3f78b47b,0xbe72b651,0x3f633c5a,0xbeebcbbb,0x3f40d0da,0xbf286605,0x3f93682a,0xbfd14d3d,0x3ebb31a0,0xbf6e46be,0x3e09cf86,0xbf7dabcc,0xbdd53db9,0xbf7e9bc9,
0x3f800000,0x0,0x3f77f110,0xbe7ee6e1,0x3f604621,0xbef6e0cb,0x3f3a7ca4,0xbf2f61a5,0x3f88f59b,0xbfd84853,0x3e9d9e78,0xbf73913f,0x3d7b2b74,0xbf7f84ab,0xbe419b37,0xbf7b61fc,
0x3f800000,0x0,0x3f772417,0xbe8586ce,0x3f5d2d53,0xbf00e7e4,0x3f33e7bc,0xbf36206c,0x3f7c5d27,0xbfdebe05,0x3e7ee6e1,0xbf77f110,0xbc490e90,0xbf7ffb11,0xbe8b9507,0xbf764d97,
0x3f800000,0x0,0x3f764d97,0xbe8b9507,0x3f59f26a,0xbf064b82,0x3f2d1469,0xbf3ca003,0x3f663375,0xbfe4aa59,0x3e419b37,0xbf7b61fc,0xbdafb680,0xbf7f0e58,0xbeb554ec,0xbf6f6830,
0x3f800000,0x0,0x3f756d97,0xbe919ddd,0x3f5695e5,0xbf0b9a6b,0x3f26050a,0xbf42de29,0x3f4f7bca,0xbfea09a7,0x3e039502,0xbf7de0b1,0xbe22abb6,0xbf7cbfc9,0xbeddbe79,0xbf66becc,
0x3f800000,0x0,0x3f748422,0xbe97a117,0x3f531849,0xbf10d3cd,0x3f1ebc12,0xbf48d8b3,0x3f38442a,0xbfeed89e,0x3d8a200a,0xbf7f6ac7,0xbe6c9a7f,0xbf791298,0xbf0242b1,0xbf5c61c7,
0x3f800000,0x0,0x3f73913f,0xbe9d9e78,0x3f4f7a1f,0xbf15f6d9,0x3f173c07,0xbf4e8d90,0x3f209ae5,0xbff31447,0x3bc90f88,0xbf7ffec4,0xbe9aa086,0xbf740bdd,0xbf14b039,0xbf5064af,
0x3f800000,0x0,0x3f7294f8,0xbea395c5,0x3f4bbbf8,0xbf1b02c6,0x3f0f8784,0xbf53fac3,0x3f088e93,0xbff6ba07,0xbd621469,0xbf7f9c18,0xbebe1d4a,0xbf6db293,0xbf26050a,0xbf42de29,
0x3f800000,0x0,0x3f718f57,0xbea986c4,0x3f47de65,0xbf1ff6cb,0x3f07a136,0xbf591e6a,0x3ee05c13,0xbff9c79d,0xbdee3876,0xbf7e4323,0xbee0924f,0xbf660f88,0xbf36206c,0xbf33e7bc,
0x3f800000,0x0,0x3f708066,0xbeaf713a,0x3f43e200,0xbf24d225,0x3eff17b2,0xbf5df6be,0x3eaf10a2,0xbffc3b28,0xbe354098,0xbf7bf531,0xbf00e7e4,0xbf5d2d53,0xbf44e3f5,0xbf239da9,
0x3f800000,0x0,0x3f6f6830,0xbeb554ec,0x3f3fc767,0xbf299415,0x3eee9479,0xbf628210,0x3e7ab273,0xbffe1324,0xbe72b651,0xbf78b47b,0xbf10d3cd,0xbf531849,0xbf5233c6,0xbf121eb0,
0x3f800000,0x0,0x3f6e46be,0xbebb31a0,0x3f3b8f3b,0xbf2e3bde,0x3eddbe79,0xbf66becc,0x3e16a905,0xbfff4e6d,0xbe97a117,0xbf748422,0xbf1ff6cb,0xbf47de65,0xbf5df6be,0xbeff17b2,
0x3f800000,0x0,0x3f6d1c1d,0xbec1071e,0x3f373a23,0xbf32c8c9,0x3ecc9b8b,0xbf6aab7b,0x3d490ab0,0xbfffec43,0xbeb554ec,0xbf6f6830,0xbf2e3bde,0xbf3b8f3b,0xbf6816a8,0xbed8106b,
0x3f800000,0x0,0x3f7ffd39,0xbc16cb58,0x3f7ff4e6,0xbc96c9b6,0x3f7fe705,0xbce22a7a,0x3fffd397,0xbd96c32c,0x3f7fba9e,0xbd3c6dd5,0x3f7f9c18,0xbd621469,0x3f7f7808,0xbd83db0a,
0x3f800000,0x0,0x3f7ff0e3,0xbcafea69,0x3f7fc38f,0xbd2fe007,0x3f7f7808,0xbd83db0a,0x3fff0e58,0xbe2fb680,0x3f7e868b,0xbddb7d37,0x3f7de0b1,0xbe039502,0x3f7d1cdd,0xbe195be0,
0x3f800000,0x0,0x3f7fdaaf,0xbd0a342f,0x3f7f6ac7,0xbd8a200a,0x3f7eb069,0xbdcefdb7,0x3ffdabcc,0xbe89cf86,0x3f7c5d3a,0xbe2bf804,0x3f7ac516,0xbe4dee60,0x3f78e3d6,0xbe6fa8b2,
0x3f800000,0x0,0x3f7fba9e,0xbd3c6dd5,0x3f7eea9d,0xbdbc3ac3,0x3f7d906e,0xbe0cec4a,0x3ffbaccd,0xbebb6ecf,0x3f7940c0,0xbe698bba,0x3f764d97,0xbe8b9507,0x3f72d4eb,0xbea21887,
0x3f800000,0x0,0x3f7f90b1,0xbd6ea038,0x3f7e4323,0xbdee3876,0x3f7c187a,0xbe3228d4,0x3ff91298,0xbeec9a7f,0x3f75341d,0xbe931f35,0x3f708066,0xbeaf713a,0x3f6afb8c,0xbecb2aae,
0x3f800000,0x0,0x3f7f5ce9,0xbd9064b4,0x3f7d7474,0xbe1008b7,0x3f7a4910,0xbe57278f,0x3ff5dec6,0xbf0e9a22,0x3f703b37,0xbeb0eacb,0x3f696591,0xbed25a09,0x3f61668a,0xbef2bd43,
0x3f800000,0x0,0x3f7f1f49,0xbda973ba,0x3f7c7eb0,0xbe28defc,0x3f7822d1,0xbe7bdba4,0x3ff21352,0xbf268f12,0x3f6a5ad9,0xbece0bea,0x3f6106f2,0xbef41f07,0x3f5627fe,0xbf0c42c9,
0x3f800000,0x0,0x3f7ed7d4,0xbdc27c39,0x3f7b61fc,0xbe419b37,0x3f75a67b,0xbe901c2c,0x3fedb293,0xbf3e1d4a,0x3f6398ac,0xbeea6681,0x3f577026,0xbf0a48ad,0x3f495521,0xbf1e1e22,
0x3f800000,0x0,0x3f7e868b,0xbddb7d37,0x3f7a1e84,0xbe5a3997,0x3f72d4eb,0xbea21887,0x3fe8bf3c,0xbf553641,0x3f5bfb34,0xbf02ef9f,0x3f4cae79,0xbf19c200,0x3f3b0629,0xbf2ecef7,
0x3f800000,0x0,0x3f7e2b72,0xbdf475c0,0x3f78b47b,0xbe72b651,0x3f6faf1b,0xbeb3dca5,0x3fe33c5a,0xbf6bcbbb,0x3f5389c7,0xbf102dd5,0x3f40d0da,0xbf286605,0x3f2b561b,0xbf3e35c5,
0x3f800000,0x0,0x3f7dc68c,0xbe06b26e,0x3f772417,0xbe8586ce,0x3f6c3624,0xbec5625c,0x3fdd2d53,0xbf80e7e4,0x3f4a4c87,0xbf1ce11f,0x3f33e7bc,0xbf36206c,0x3f1a6293,0xbf4c3578,
0x3f800000,0x0,0x3f7d57de,0xbe1324ca,0x3f756d97,0xbe919ddd,0x3f686b39,0xbed6a399,0x3fd695e5,0xbf8b9a6b,0x3f404c5c,0xbf28fd41,0x3f26050a,0xbf42de29,0x3f084b92,0xbf58b3a1,
0x3f800000,0x0,0x3f7cdf6c,0xbe1f917b,0x3f73913f,0xbe9d9e78,0x3f644fac,0xbee79a5d,0x3fcf7a1f,0xbf95f6d9,0x3f3592e7,0xbf34768f,0x3f173c07,0xbf4e8d90,0x3eea6681,0xbf6398ac,
0x3f800000,0x0,0x3f7c5d3a,0xbe2bf804,0x3f718f57,0xbea986c4,0x3f5fe4e9,0xbef840c8,0x3fc7de65,0xbf9ff6cb,0x3f2a2a80,0xbf3f41fc,0x3f07a136,0xbf591e6a,0x3ec27b55,0xbf6cd007,
0x3f800000,0x0,0x3f7bd14d,0xbe3857ec,0x3f6f6830,0xbeb554ec,0x3f5b2c79,0xbf044889,0x3fbfc767,0xbfa99415,0x3f1e1e22,0xbf495521,0x3eee9479,0xbf628210,0x3e9920fe,0xbf74484b,
0x3f800000,0x0,0x3f7b3bab,0xbe44b0b9,0x3f6d1c1d,0xbec1071e,0x3f5627fe,0xbf0c42c9,0x3fb73a23,0xbfb2c8c9,0x3f11796b,0xbf52a649,0x3ecc9b8b,0xbf6aab7b,0x3e5d4b1a,0xbf79f35e,
0x3f800000,0x0,0x3f7a9c59,0xbe5101f1,0x3f6aab7b,0xbecc9b8b,0x3f50d937,0xbf140c5f,0x3fae3bde,0xbfbb8f3b,0x3f044889,0xbf5b2c79,0x3ea986c4,0xbf718f57,0x3e06b26e,0xbf7dc68c,
0x3f800000,0x0,0x3f79f35e,0xbe5d4b1a,0x3f6816a8,0xbed8106b,0x3f4b41fa,0xbf1ba299,0x3fa4d225,0xbfc3e200,0x3eed3063,0xbf62df7b,0x3e8586ce,0xbf772417,0x3d3c6dd5,0xbf7fba9e,
0x3f800000,0x0,0x3f7940c0,0xbe698bba,0x3f655e0b,0xbee363fa,0x3f456439,0xbf2302d3,0x3f9b02c6,0xbfcbbbf8,0x3ed0eb2a,0xbf69b7e4,0x3e419b37,0xbf7b61fc,0xbd2351cb,0xbf7fcbe2,
0x3f800000,0x0,0x3f788486,0xbe75c35a,0x3f628210,0xbeee9479,0x3f3f41fc,0xbf2a2a80,0x3f90d3cd,0xbfd31849,0x3eb3dca5,0xbf6faf1b,0x3dee3876,0xbf7e4323,0xbe007745,0xbf7dfa38,
0x3f800000,0x0,0x3f77beb7,0xbe80f8c0,0x3f5f8327,0xbef9a02d,0x3f38dd65,0xbf311722,0x3f864b82,0xbfd9f26a,0x3e9620d2,0xbf74bf62,0x3d2fe007,0xbf7fc38f,0xbe57278f,0xbf7a4910,
0x3f800000,0x0,0x3f76ef5b,0xbe870ada,0x3f5c61c7,0xbf0242b1,0x3f3238aa,0xbf37c655,0x3f76e0cb,0xbfe04621,0x3e6fa8b2,0xbf78e3d6,0xbcfb49ba,0xbf7fe129,0xbe9620d2,0xbf74bf62,
0x3f800000,0x0,0x3f76167a,0xbe8d17c0,0x3f591e6a,0xbf07a136,0x3f2b561b,0xbf3e35c5,0x3f60924f,0xbfe60f88,0x3e3228d4,0xbf7c187a,0xbdd53db9,0xbf7e9bc9,0xbebf926f,0xbf6d67a1,
0x3f800000,0x0,0x3f75341d,0xbe931f35,0x3f55b993,0xbf0cead0,0x3f24381a,0xbf446337,0x3f49b953,0xbfeb4b0c,0x3de7fa9a,0xbf7e5a38,0xbe354098,0xbf7bf531,0xbee79a5d,0xbf644fac,
0x3f800000,0x0,0x3f74484b,0xbe9920fe,0x3f5233c6,0xbf121eb0,0x3f1ce11f,0xbf4a4c87,0x3f3263ef,0xbfeff573,0x3d55880e,0xbf7fa6e3,0xbe7ee6e1,0xbf77f110,0xbf06f686,0xbf5988ad,
0x3f800000,0x0,0x3f73530e,0xbe9f1cdf,0x3f4e8d90,0xbf173c07,0x3f1553b7,0xbf4fefa8,0x3f1aa086,0xbff40bdd,0xbc16cb58,0xbf7ffd39,0xbea395c5,0xbf7294f8,0xbf19210f,0xbf4d26fd,
0x3f800000,0x0,0x3f725470,0xbea5129f,0x3f4ac77f,0xbf1c420c,0x3f0d9281,0xbf554aa4,0x3f027dc0,0xbff78bc5,0xbd9064b4,0xbf7f5ce9,0xbec6d529,0xbf6be858,0xbf2a2a80,0xbf3f41fc,
0x3f800000,0x0,0x3f714c7a,0xbeab0201,0x3f46e22a,0xbf212ff9,0x3f05a02c,0xbf5a5ba0,0x3ed41501,0xbffa7302,0xbe06b26e,0xbf7dc68c,0xbee900b7,0xbf63f473,0xbf39f2ac,0xbf2ff3e6,
0x3f800000,0x0,0x3f703b37,0xbeb0eacb,0x3f42de29,0xbf26050a,0x3efafef7,0xbf5f20db,0x3ea2abb6,0xbffcbfc9,0xbe44b0b9,0xbf7b3bab,0xbf04f484,0xbf5ac450,0xbf485bca,0xbf1f599f,
0x3f800000,0x0,0x3f6f20b0,0xbeb6ccc3,0x3f3ebc1b,0xbf2ac082,0x3eea6681,0xbf6398ac,0x3e61bc2e,0xbffe70b0,0xbe80f8c0,0xbf77beb7,0xbf14b039,0xbf5064af,0xbf554aa4,0xbf0d9281,
0x3f800000,0x0,0x3f6dfcf2,0xbebca7af,0x3f3a7ca4,0xbf2f61a5,0x3ed97cb9,0xbf67c187,0x3dfb2b74,0xbfff84ab,0xbe9f1cdf,0xbf73530e,0xbf239da9,0xbf44e3f5,0xbf60a6cf,0xbef58035,
0x3f800000,0x0,0x3f6cd007,0xbec27b55,0x3f36206c,0xbf33e7bc,0x3ec8477c,0xbf6b99fb,0x3cc90e90,0xbffffb11,0xbebca7af,0xbf6dfcf2,0xbf31a81d,0xbf385216,0xbf6a5ad9,0xbece0bea,
0x3f800000,0x0,0x0,0x0,0x0,0x0,0x0,0x0,0x0,0x0,0x0,0x0,0x0,0x0,0x0,0x0,
0x0,0x0,0x0,0x0,0x0,0x0,0x0,0x0,0x0,0x0,0x0,0x0,0x0,0x0,0x0,0x0,
0x0,0x0,0x3e000000,0xbf20dff7,0x3ed0c429,0x0,0x3e000000,0x3e61f78b,0x3e0a8bd4,0x0,0x3e000000,0x3d5413cd,0x3d5df9ad,0x0,0x3e000000,0x3cf043ab,
0x0,0x0,0x3e000000,0x3ccbafaf,0xbd5df9ad,0x0,0x3e000000,0x3cf043ab,0xbe0a8bd4,0x0,0x3e000000,0x3d5413cd,0xbed0c429,0x0,0x3e000000,0x3e61f78b,
0x0,0x0,0x0,0x0,0x3f000000,0x0,0x0,0x3f000000,0x0,0x0,0x0,0x0,0x0,0x0,0x0,0x0,
0x0,0x0,0x0,0x0,0x0,0x0,0x0,0x0,0x0,0x0,0x0,0x0,0x3f000000,0x0,0x0,0xbf000000,
0x0,0x0,0x3e000000,0xbe3f90c7,0xbe8b7e3f,0x0,0x3e000000,0xbeb641af,0x3ea73d75,0x0,0x3e000000,0x3e9a827a,0x3da61ad1,0x0,0x3e000000,0x3dd906bd,
0x0,0x0,0x3e000000,0x3dab0dc1,0xbda61ad1,0x0,0x3e000000,0x3dd906bd,0xbea73d75,0x0,0x3e000000,0x3e9a827a,0x3e8b7e3f,0x0,0x3e000000,0xbeb641af,
0x0,0x0,0x0,0x0,0x0,0x0,0x0,0x0,0x3f000000,0x0,0x0,0x3f000000,0x0,0x0,0x0,0x0,
0x0,0x0,0x0,0x0,0x0,0x0,0x0,0x0,0x3f000000,0x0,0x0,0xbf000000,0x0,0x0,0x0,0x0,
0x0,0x0,0x3e000000,0xbdab0dc1,0xbda61ad1,0x0,0x3e000000,0xbdd906bd,0xbea73d75,0x0,0x3e000000,0xbe9a827a,0x3e8b7e3f,0x0,0x3e000000,0x3eb641af,
0x0,0x0,0x3e000000,0x3e3f90c7,0xbe8b7e3f,0x0,0x3e000000,0x3eb641af,0x3ea73d75,0x0,0x3e000000,0xbe9a827a,0x3da61ad1,0x0,0x3e000000,0xbdd906bd,
0x0,0x0,0x0,0x0,0x0,0x0,0x0,0x0,0x0,0x0,0x0,0x0,0x3f000000,0x0,0x0,0x3f000000,
0x0,0x0,0x0,0x0,0x3f000000,0x0,0x0,0xbf000000,0x0,0x0,0x0,0x0,0x0,0x0,0x0,0x0,
0x0,0x0,0x3e000000,0xbccbafaf,0xbd5df9ad,0x0,0x3e000000,0xbcf043ab,0xbe0a8bd4,0x0,0x3e000000,0xbd5413cd,0xbed0c429,0x0,0x3e000000,0xbe61f78b,
0x0,0x0,0x3e000000,0x3f20dff7,0x3ed0c429,0x0,0x3e000000,0xbe61f78b,0x3e0a8bd4,0x0,0x3e000000,0xbd5413cd,0x3d5df9ad,0x0,0x3e000000,0xbcf043ab,
};

struct Params {
    const __nv_bfloat16 *wr, *wi, *lre, *lim, *ldt, *dsk;
    float* out;
};

struct cf { float x, y; };
#define YIELD() asm volatile("pmevent 1;")
#define YS 14
#define YIELD_S1() do { if (YS & 1) YIELD(); } while (0)
#define YIELD_S2() do { if (YS & 2) YIELD(); } while (0)
#define YIELD_S3() do { if (YS & 4) YIELD(); } while (0)
__device__ __forceinline__ uint32_t smem_u32(const void* p) { return (uint32_t)__cvta_generic_to_shared(p); }
__device__ __forceinline__ void mbar_init(uint32_t a, uint32_t c) { asm volatile("mbarrier.init.shared::cta.b64 [%0], %1;" ::"r"(a), "r"(c) : "memory"); }
__device__ __forceinline__ void mbar_expect_tx(uint32_t a, uint32_t b) { asm volatile("mbarrier.arrive.expect_tx.shared::cta.b64 _, [%0], %1;" ::"r"(a), "r"(b) : "memory"); }
__device__ __forceinline__ void mbar_arrive(uint32_t a) { asm volatile("mbarrier.arrive.shared::cta.b64 _, [%0];" ::"r"(a) : "memory"); }
__device__ __forceinline__ void warp_arrive(uint32_t a) {
    __syncwarp();
    asm volatile("{.reg .pred p; elect.sync _|p, 0xffffffff; @p mbarrier.arrive.shared::cta.b64 _, [%0];}" ::"r"(a) : "memory");
}
__device__ __forceinline__ uint32_t mbar_try(uint32_t a, uint32_t ph) {
    uint32_t ok;
    asm volatile("{.reg .pred p; mbarrier.try_wait.parity.shared::cta.b64 p, [%1], %2; selp.u32 %0, 1, 0, p;}" : "=r"(ok) : "r"(a), "r"(ph) : "memory");
    return ok;
}
__device__ __forceinline__ void mbar_wait(uint32_t a, uint32_t ph) {
    uint32_t ok, n = 0;
    do { ok = mbar_try(a, ph); } while (!ok && ++n < SPIN_LIMIT);
}
__device__ __forceinline__ void mbar_wait_fast(uint32_t a, uint32_t ph) { if (!mbar_try(a, ph)) mbar_wait(a, ph); }
__device__ __forceinline__ unsigned ld_rlx(const unsigned* p) { unsigned v; asm volatile("ld.relaxed.gpu.global.u32 %0, [%1];" : "=r"(v) : "l"(p) : "memory"); return v; }
__device__ __forceinline__ void wait_cnt(const unsigned* p, unsigned target) {
    unsigned n = 0;
    while ((int)(ld_rlx(p) - target) < 0 && ++n < SPIN_LIMIT) __nanosleep(20);
}
__device__ __forceinline__ void red_hint(unsigned* p) { asm volatile("red.relaxed.gpu.global.add.u32 [%0], 1;" ::"l"(p) : "memory"); }
__device__ __forceinline__ void fence_async() { asm volatile("fence.proxy.async.global;" ::: "memory"); }
__device__ __forceinline__ void fence_async_sm() { asm volatile("fence.proxy.async.shared::cta;" ::: "memory"); }
#define bar_sync(id, n) asm volatile("bar.sync %0, %1;" ::"n"(id), "n"(n) : "memory")
#define bar_arrive(id, n) asm volatile("bar.arrive %0, %1;" ::"n"(id), "n"(n) : "memory")
__device__ __forceinline__ bool elect_one() {
    uint32_t r;
    asm volatile("{.reg .pred p; elect.sync _|p, 0xffffffff; selp.u32 %0, 1, 0, p;}" : "=r"(r));
    return r != 0;
}

__device__ __forceinline__ void tma2d(uint32_t dst, const CUtensorMap* m, int c0, int c1, uint32_t bar) {
    asm volatile("cp.async.bulk.tensor.2d.shared::cluster.global.mbarrier::complete_tx::bytes [%0], [%1, {%3,%4}], [%2];" ::"r"(dst), "l"(m), "r"(bar), "r"(c0), "r"(c1) : "memory");
}
__device__ __forceinline__ void tma3d(uint32_t dst, const CUtensorMap* m, int c0, int c1, int c2, uint32_t bar) {
    asm volatile("cp.async.bulk.tensor.3d.shared::cluster.global.mbarrier::complete_tx::bytes [%0], [%1, {%3,%4,%5}], [%2];" ::"r"(dst), "l"(m), "r"(bar), "r"(c0), "r"(c1), "r"(c2) : "memory");
}
__device__ __forceinline__ void tma2d_mc(uint32_t dst, const CUtensorMap* m, int c0, int c1, uint32_t bar) {
    asm volatile("cp.async.bulk.tensor.2d.shared::cluster.global.mbarrier::complete_tx::bytes.multicast::cluster [%0], [%1, {%3,%4}], [%2], %5;" ::"r"(dst), "l"(m), "r"(bar), "r"(c0), "r"(c1), "h"((uint16_t)3) : "memory");
}
__device__ __forceinline__ void tma4d_mc(uint32_t dst, const CUtensorMap* m, int c0, int c1, int c2, int c3, uint32_t bar) {
    asm volatile("cp.async.bulk.tensor.4d.shared::cluster.global.mbarrier::complete_tx::bytes.multicast::cluster [%0], [%1, {%3,%4,%5,%6}], [%2], %7;" ::"r"(dst), "l"(m), "r"(bar), "r"(c0), "r"(c1), "r"(c2), "r"(c3), "h"((uint16_t)3) : "memory");
}
__device__ __forceinline__ void tma4d(uint32_t dst, const CUtensorMap* m, int c0, int c1, int c2, int c3, uint32_t bar) {
    asm volatile("cp.async.bulk.tensor.4d.shared::cluster.global.mbarrier::complete_tx::bytes [%0], [%1, {%3,%4,%5,%6}], [%2];" ::"r"(dst), "l"(m), "r"(bar), "r"(c0), "r"(c1), "r"(c2), "r"(c3) : "memory");
}
__device__ __forceinline__ void tma2d_st(const CUtensorMap* m, int c0, int c1, uint32_t src) {
    asm volatile("cp.async.bulk.tensor.2d.global.shared::cta.bulk_group [%0, {%2,%3}], [%1];" ::"l"(m), "r"(src), "r"(c0), "r"(c1) : "memory");
}
__device__ __forceinline__ void tma3d_st(const CUtensorMap* m, int c0, int c1, int c2, uint32_t src) {
    asm volatile("cp.async.bulk.tensor.3d.global.shared::cta.bulk_group [%0, {%2,%3,%4}], [%1];" ::"l"(m), "r"(src), "r"(c0), "r"(c1), "r"(c2) : "memory");
}
__device__ __forceinline__ void tma5d(uint32_t dst, const CUtensorMap* m, int c0, int c1, int c2, int c3, int c4, uint32_t bar) {
    asm volatile("cp.async.bulk.tensor.5d.shared::cluster.global.mbarrier::complete_tx::bytes [%0], [%1, {%3,%4,%5,%6,%7}], [%2];" ::"r"(dst), "l"(m), "r"(bar), "r"(c0), "r"(c1), "r"(c2), "r"(c3), "r"(c4) : "memory");
}
__device__ __forceinline__ void tma5d_mc(uint32_t dst, const CUtensorMap* m, int c0, int c1, int c2, int c3, int c4, uint32_t bar) {
    asm volatile("cp.async.bulk.tensor.5d.shared::cluster.global.mbarrier::complete_tx::bytes.multicast::cluster [%0], [%1, {%3,%4,%5,%6,%7}], [%2], %8;" ::"r"(dst), "l"(m), "r"(bar), "r"(c0), "r"(c1), "r"(c2), "r"(c3), "r"(c4), "h"((uint16_t)3) : "memory");
}
__device__ __forceinline__ void bulk_pf(const void* src, uint32_t n) { asm volatile("cp.async.bulk.prefetch.L2.global [%0], %1;" ::"l"(src), "r"(n) : "memory"); }
__device__ __forceinline__ void tma4d_pf(const CUtensorMap* m, int c0, int c1, int c2, int c3) {
    asm volatile("cp.async.bulk.prefetch.tensor.4d.L2.global [%0, {%1,%2,%3,%4}];" ::"l"(m), "r"(c0), "r"(c1), "r"(c2), "r"(c3) : "memory");
}
__device__ __forceinline__ void tma5d_pf(const CUtensorMap* m, int c0, int c1, int c2, int c3, int c4) {
    asm volatile("cp.async.bulk.prefetch.tensor.5d.L2.global [%0, {%1,%2,%3,%4,%5}];" ::"l"(m), "r"(c0), "r"(c1), "r"(c2), "r"(c3), "r"(c4) : "memory");
}
__device__ __forceinline__ void bulk_ld(uint32_t dst, const void* src, uint32_t n, uint32_t bar) {
    asm volatile("cp.async.bulk.shared::cluster.global.mbarrier::complete_tx::bytes [%0], [%1], %2, [%3];" ::"r"(dst), "l"(src), "r"(n), "r"(bar) : "memory");
}
__device__ __forceinline__ void bulk_st(void* dst, uint32_t src, uint32_t n) {
    asm volatile("cp.async.bulk.global.shared::cta.bulk_group [%0], [%1], %2;" ::"l"(dst), "r"(src), "r"(n) : "memory");
}
__device__ __forceinline__ void bulk_commit() { asm volatile("cp.async.bulk.commit_group;" ::: "memory"); }
__device__ __forceinline__ void bulk_wait_read() { asm volatile("cp.async.bulk.wait_group.read 0;" ::: "memory"); }
__device__ __forceinline__ void bulk_wait_all() { asm volatile("cp.async.bulk.wait_group 0;" ::: "memory"); }
__device__ __forceinline__ void stsm4(uint32_t a, uint32_t r0, uint32_t r1, uint32_t r2, uint32_t r3) {
    asm volatile("stmatrix.sync.aligned.m8n8.x4.shared.b16 [%0], {%1,%2,%3,%4};" ::"r"(a), "r"(r0), "r"(r1), "r"(r2), "r"(r3) : "memory");
}
__device__ __forceinline__ void sts128(uint32_t a, uint32_t r0, uint32_t r1, uint32_t r2, uint32_t r3) {
    asm volatile("st.shared.v4.b32 [%0], {%1,%2,%3,%4};" ::"r"(a), "r"(r0), "r"(r1), "r"(r2), "r"(r3) : "memory");
}
__device__ __forceinline__ void lds128f(uint32_t a, float& x, float& y, float& z, float& u) { asm volatile("ld.shared.v4.f32 {%0,%1,%2,%3}, [%4];" : "=f"(x), "=f"(y), "=f"(z), "=f"(u) : "r"(a) : "memory"); }
__device__ __forceinline__ cf lds_cf(uint32_t a) { cf v; asm volatile("ld.shared.v2.f32 {%0,%1}, [%2];" : "=f"(v.x), "=f"(v.y) : "r"(a) : "memory"); return v; }
__device__ __forceinline__ void stg128(const void* a, uint32_t r0, uint32_t r1, uint32_t r2, uint32_t r3) {
    asm volatile("st.global.v4.b32 [%0], {%1,%2,%3,%4};" ::"l"(a), "r"(r0), "r"(r1), "r"(r2), "r"(r3) : "memory");
}
__device__ __forceinline__ int fresh_lane() { int v; asm volatile("mov.u32 %0, %%laneid;" : "=r"(v)); return v; }
__device__ __forceinline__ uint32_t opaque32(uint32_t v) { asm volatile("" : "+r"(v)); return v; }
__device__ __forceinline__ const uint8_t* padd(const void* base, uint32_t off) {
    uint64_t r;
    asm("{.reg .u32 l, h; mov.b64 {l, h}, %1; add.cc.u32 l, l, %2; addc.u32 h, h, 0; mov.b64 %0, {l, h};}" : "=l"(r) : "l"(base), "r"(off));
    return (const uint8_t*)r;
}
template <int N, int STRIDE> __device__ __forceinline__ void ldtab(uint32_t (&v)[4 * N], uint32_t off) {
    const uint8_t* a = padd(g_tab, off);
#pragma unroll
    for (int i = 0; i < N; i++)
        asm volatile("ld.global.nc.v4.b32 {%0,%1,%2,%3}, [%4];" : "=r"(v[4 * i]), "=r"(v[4 * i + 1]), "=r"(v[4 * i + 2]), "=r"(v[4 * i + 3]) : "l"(a + i * STRIDE));
}
template <int STRIDE> __device__ __forceinline__ void ldtab_cf(cf (&t)[8], uint32_t off) {
    uint32_t v[16];
    ldtab<4, STRIDE>(v, off);
#pragma unroll
    for (int i = 0; i < 8; i++) t[i] = {__uint_as_float(v[2 * i]), __uint_as_float(v[2 * i + 1])};
}
__device__ __forceinline__ uint32_t lds16(uint32_t a) { uint32_t v; asm volatile("ld.shared.u16 %0, [%1];" : "=r"(v) : "r"(a)); return v; }
__device__ __forceinline__ unsigned get_epoch(uint32_t bars) {
    mbar_wait(bars + B_EP, 0);
    unsigned e;
    asm volatile("ld.shared.u32 %0, [%1];" : "=r"(e) : "r"(bars + B_EPOCH) : "memory");
    return e;
}
__device__ __forceinline__ void sts64(uint32_t a, uint32_t x, uint32_t y) { asm volatile("st.shared.v2.b32 [%0], {%1,%2};" ::"r"(a), "r"(x), "r"(y) : "memory"); }
__device__ __forceinline__ uint32_t pk(float lo, float hi) { uint32_t r; asm("cvt.rn.bf16x2.f32 %0, %1, %2;" : "=r"(r) : "f"(hi), "f"(lo)); return r; }
__device__ __forceinline__ float bf2f(unsigned short v) { return __uint_as_float((uint32_t)v << 16); }

__device__ __forceinline__ uint64_t mkdesc(uint32_t addr, uint32_t lbo, uint32_t sbo, uint32_t swz) {
    return (uint64_t)((addr & 0x3FFFF) >> 4) | ((uint64_t)(lbo >> 4) << 16) | ((uint64_t)(sbo >> 4) << 32) | ((uint64_t)swz << 62);
}
__device__ __forceinline__ uint64_t opaque(uint64_t v) { asm volatile("" : "+l"(v)); return v; }
__device__ __forceinline__ void wg_fence() { asm volatile("wgmma.fence.sync.aligned;" ::: "memory"); }
__device__ __forceinline__ void wg_commit() { asm volatile("wgmma.commit_group.sync.aligned;" ::: "memory"); }
template <int N> __device__ __forceinline__ void wg_wait() { asm volatile("wgmma.wait_group.sync.aligned %0;" ::"n"(N) : "memory"); }
template <int N> __device__ __forceinline__ void pin(float (&d)[N]) {
#pragma unroll
    for (int i = 0; i < N; i++) asm volatile("" : "+f"(d[i])::"memory");
}
template <int N> __device__ __forceinline__ void pinu(uint32_t (&d)[N]) {
#pragma unroll
    for (int i = 0; i < N; i++) asm volatile("" : "+r"(d[i])::"memory");
}

#define R8(d, o) "+f"(d[o]), "+f"(d[o + 1]), "+f"(d[o + 2]), "+f"(d[o + 3]), "+f"(d[o + 4]), "+f"(d[o + 5]), "+f"(d[o + 6]), "+f"(d[o + 7])
#define L8 "%0,%1,%2,%3,%4,%5,%6,%7"
#define L32 L8 ",%8,%9,%10,%11,%12,%13,%14,%15,%16,%17,%18,%19,%20,%21,%22,%23,%24,%25,%26,%27,%28,%29,%30,%31"
#define L56 L32 ",%32,%33,%34,%35,%36,%37,%38,%39,%40,%41,%42,%43,%44,%45,%46,%47,%48,%49,%50,%51,%52,%53,%54,%55"
#define L64 L56 ",%56,%57,%58,%59,%60,%61,%62,%63"

template <int O, int TA, int TB, int N> __device__ __forceinline__ void mma128_ss(float (&d)[N], uint64_t da, uint64_t db, int sc) {
    asm volatile("{.reg .pred p; setp.ne.b32 p, %66, 0;\n"
                 "wgmma.mma_async.sync.aligned.m64n128k16.f32.bf16.bf16 {" L64 "}, %64, %65, p, 1, 1, %67, %68;}"
                 : R8(d, O), R8(d, O + 8), R8(d, O + 16), R8(d, O + 24), R8(d, O + 32), R8(d, O + 40), R8(d, O + 48), R8(d, O + 56)
                 : "l"(da), "l"(db), "r"(sc), "n"(TA), "n"(TB));
}
template <int O, int TB> __device__ __forceinline__ void mma128_rs(float (&d)[128], uint32_t a0, uint32_t a1, uint32_t a2, uint32_t a3, uint64_t db, int sc) {
    asm volatile("{.reg .pred p; setp.ne.b32 p, %69, 0;\n"
                 "wgmma.mma_async.sync.aligned.m64n128k16.f32.bf16.bf16 {" L64 "}, {%64,%65,%66,%67}, %68, p, 1, 1, %70;}"
                 : R8(d, O), R8(d, O + 8), R8(d, O + 16), R8(d, O + 24), R8(d, O + 32), R8(d, O + 40), R8(d, O + 48), R8(d, O + 56)
                 : "r"(a0), "r"(a1), "r"(a2), "r"(a3), "l"(db), "r"(sc), "n"(TB));
}
template <int TB> __device__ __forceinline__ void mma64_rs(float (&d)[32], uint32_t a0, uint32_t a1, uint32_t a2, uint32_t a3, uint64_t db, int sc) {
    asm volatile("{.reg .pred p; setp.ne.b32 p, %37, 0;\n"
                 "wgmma.mma_async.sync.aligned.m64n64k16.f32.bf16.bf16 {" L32 "}, {%32,%33,%34,%35}, %36, p, 1, 1, %38;}"
                 : R8(d, 0), R8(d, 8), R8(d, 16), R8(d, 24)
                 : "r"(a0), "r"(a1), "r"(a2), "r"(a3), "l"(db), "r"(sc), "n"(TB));
}
__device__ __forceinline__ void mma112_ss(float (&d)[64], uint64_t da, uint64_t db, int sc) {
    asm volatile("{.reg .pred p; setp.ne.b32 p, %58, 0;\n"
                 "wgmma.mma_async.sync.aligned.m64n112k16.f32.bf16.bf16 {" L56 "}, %56, %57, p, 1, 1, 0, 1;}"
                 : R8(d, 8), R8(d, 16), R8(d, 24), R8(d, 32), R8(d, 40), R8(d, 48), R8(d, 56)
                 : "l"(da), "l"(db), "r"(sc));
}
__device__ __forceinline__ void mma16_rs(float (&d)[64], uint32_t a0, uint32_t a1, uint32_t a2, uint32_t a3, uint64_t db, int sc) {
    asm volatile("{.reg .pred p; setp.ne.b32 p, %13, 0;\n"
                 "wgmma.mma_async.sync.aligned.m64n16k16.f32.bf16.bf16 {" L8 "}, {%8,%9,%10,%11}, %12, p, 1, 1, 1;}"
                 : R8(d, 0)
                 : "r"(a0), "r"(a1), "r"(a2), "r"(a3), "l"(db), "r"(sc));
}

__device__ __forceinline__ cf cmul(cf a, cf b) { return {fmaf(a.x, b.x, -a.y * b.y), fmaf(a.x, b.y, a.y * b.x)}; }
__device__ __forceinline__ cf cmulc(cf a, cf b) { return {fmaf(a.x, b.x, a.y * b.y), fmaf(a.y, b.x, -a.x * b.y)}; }
__device__ __forceinline__ cf cfma(cf a, cf b, cf c) { return {fmaf(a.x, b.x, fmaf(-a.y, b.y, c.x)), fmaf(a.x, b.y, fmaf(a.y, b.x, c.y))}; }
__device__ __forceinline__ cf csq(cf a) { return {fmaf(a.x, a.x, -a.y * a.y), (a.x * a.y) * 2.f}; }
__device__ __forceinline__ cf csel(int c, cf a, cf b) {
    cf r;
    asm("{.reg .pred p; setp.ne.s32 p, %2, 0; selp.f32 %0, %3, %5, p; selp.f32 %1, %4, %6, p;}" : "=f"(r.x), "=f"(r.y) : "r"(c), "f"(a.x), "f"(a.y), "f"(b.x), "f"(b.y));
    return r;
}
__device__ __forceinline__ cf cadd(cf a, cf b) { return {a.x + b.x, a.y + b.y}; }
__device__ __forceinline__ cf csub(cf a, cf b) { return {a.x - b.x, a.y - b.y}; }
__device__ __forceinline__ cf twice_minus(cf a, cf s) { return {fmaf(2.f, a.x, -s.x), fmaf(2.f, a.y, -s.y)}; }
__device__ __forceinline__ cf twid(int m, int M) {
    int r = ((m + M / 2) & (M - 1)) - M / 2;
    float s, c;
    __sincosf((float)r * (-6.283185307179586f / (float)M), &s, &c);
    return {c, s};
}
struct c2 { cf a, b; };
#define YP1 3
#define YP2 0
#define YP3 3
template <int Y> __device__ __forceinline__ void fin(c2& u) { if (Y & 1) asm volatile("pmevent 1;" : "+f"(u.a.x), "+f"(u.a.y), "+f"(u.b.x), "+f"(u.b.y)); }
template <int Y> __device__ __forceinline__ void fin(c2& u, c2& v) {
    if (Y & 2) asm volatile("pmevent 1;" : "+f"(u.a.x), "+f"(u.a.y), "+f"(u.b.x), "+f"(u.b.y), "+f"(v.a.x), "+f"(v.a.y), "+f"(v.b.x), "+f"(v.b.y));
}
__device__ __forceinline__ c2 mul2(c2 u, cf t) { return {cmul(u.a, t), cmul(u.b, t)}; }
__device__ __forceinline__ c2 mul2(c2 u, c2 t) { return {cmul(u.a, t.a), cmul(u.b, t.b)}; }
__device__ __forceinline__ c2 fma2(c2 u, cf t, c2 c) { return {cfma(u.a, t, c.a), cfma(u.b, t, c.b)}; }
__device__ __forceinline__ c2 fma2(c2 u, c2 t, c2 c) { return {cfma(u.a, t.a, c.a), cfma(u.b, t.b, c.b)}; }
__device__ __forceinline__ c2 twm2(c2 u, c2 s) { return {twice_minus(u.a, s.a), twice_minus(u.b, s.b)}; }
template <int Y> __device__ __forceinline__ void bfly(c2& u, c2& v) { const c2 t = u; u = {cadd(t.a, v.a), cadd(t.b, v.b)}; v = {csub(t.a, v.a), csub(t.b, v.b)}; fin<Y>(u, v); }
template <int Y> __device__ __forceinline__ void bfly_mi(c2& u, c2& v) {
    const c2 t = u, z = v;
    u = {{t.a.x + z.a.y, t.a.y - z.a.x}, {t.b.x + z.b.y, t.b.y - z.b.x}};
    v = {{t.a.x - z.a.y, t.a.y + z.a.x}, {t.b.x - z.b.y, t.b.y + z.b.x}};
    fin<Y>(u, v);
}
template <int Y> __device__ __forceinline__ void bfly_s(c2& u, c2& v) {
    const float s = 0.70710678118654752f;
    const c2 t = u, z = v;
    u = {{fmaf(s, z.a.x, t.a.x), fmaf(s, z.a.y, t.a.y)}, {fmaf(s, z.b.x, t.b.x), fmaf(s, z.b.y, t.b.y)}};
    v = {{fmaf(-s, z.a.x, t.a.x), fmaf(-s, z.a.y, t.a.y)}, {fmaf(-s, z.b.x, t.b.x), fmaf(-s, z.b.y, t.b.y)}};
    fin<Y>(u, v);
}
template <int Y, class T> __device__ __forceinline__ void bfly_tw(c2& u0, c2& v0, T t0, c2& u1, c2& v1, T t1) {
    v0 = fma2(v0, t0, u0); fin<Y>(v0);
    v1 = fma2(v1, t1, u1); fin<Y>(v1);
    const c2 a = twm2(u0, v0), b = twm2(u1, v1);
    u0 = v0; u1 = v1; v0 = a; v1 = b;
    fin<Y>(v0, v1);
}
template <bool TW, int Y> __device__ __forceinline__ void dft8(c2 (&v)[8], const cf (&tw)[8]) {
    if (TW) {
#pragma unroll
        for (int n = 1; n < 4; n++) { v[n] = mul2(v[n], tw[n]); fin<Y>(v[n]); }
        bfly_tw<Y>(v[0], v[4], tw[4], v[2], v[6], tw[6]);
        bfly_tw<Y>(v[1], v[5], tw[5], v[3], v[7], tw[7]);
    } else {
#pragma unroll
        for (int n = 0; n < 4; n++) bfly<Y>(v[n], v[n + 4]);
    }
    bfly<Y>(v[0], v[2]); bfly_mi<Y>(v[4], v[6]);
    bfly<Y>(v[1], v[3]); bfly_mi<Y>(v[5], v[7]);
    v[5] = {{v[5].a.x + v[5].a.y, v[5].a.y - v[5].a.x}, {v[5].b.x + v[5].b.y, v[5].b.y - v[5].b.x}};
    v[7] = {{v[7].a.y - v[7].a.x, -v[7].a.x - v[7].a.y}, {v[7].b.y - v[7].b.x, -v[7].b.x - v[7].b.y}};
    fin<Y>(v[5], v[7]);
    bfly<Y>(v[0], v[1]); bfly_s<Y>(v[4], v[5]); bfly_mi<Y>(v[2], v[3]); bfly_s<Y>(v[6], v[7]);
    const c2 t1 = v[1], t3 = v[3];
    v[1] = v[4]; v[4] = t1; v[3] = v[6]; v[6] = t3;
}

__device__ __forceinline__ void gather(uint64_t (&fv)[4], const uint8_t* a, int n) {
    asm volatile("{.reg .pred p0, p1, p2, p3;\n"
                 "setp.ge.s32 p0, %5, 0; setp.ge.s32 p1, %5, 4; setp.ge.s32 p2, %5, 8; setp.ge.s32 p3, %5, 12;\n"
                 "@p0 ld.relaxed.gpu.global.b64 %0, [%4]; @p1 ld.relaxed.gpu.global.b64 %1, [%4+-32768];\n"
                 "@p2 ld.relaxed.gpu.global.b64 %2, [%4+-65536]; @p3 ld.relaxed.gpu.global.b64 %3, [%4+-98304];}"
                 : "+l"(fv[0]), "+l"(fv[1]), "+l"(fv[2]), "+l"(fv[3]) : "l"(a), "r"(n) : "memory");
}
__device__ __forceinline__ cf as_cf(uint64_t v) { cf r; asm("mov.b64 {%0,%1}, %2;" : "=f"(r.x), "=f"(r.y) : "l"(v)); return r; }
template <int H> __device__ __forceinline__ void prescale(float (&u)[64], const float (&d)[128], cf gam) {
#pragma unroll
    for (int i = 0; i < 32; i += 2) {
        const int r = 2 * i + 2 * H;
        c2 v = mul2(c2{{d[r], -d[64 + r]}, {d[r + 1], -d[65 + r]}}, gam);
        if (YS & 2) asm volatile("pmevent 1;" : "+f"(v.a.x), "+f"(v.a.y), "+f"(v.b.x), "+f"(v.b.y));
        u[i] = v.a.x; u[32 + i] = v.a.y; u[i + 1] = v.b.x; u[33 + i] = v.b.y;
    }
}
__device__ __forceinline__ void scan2(const float (&u)[64], cf lam, cf st, const uint8_t* hptr, uint32_t hm, uint32_t hb, uint32_t& keep) {
    uint32_t hp[32];
#pragma unroll
    for (int jj = 0; jj < 4; jj++) {
        cf v[8];
#pragma unroll
        for (int i = 0; i < 8; i++) v[i] = st = cfma(lam, st, {u[8 * jj + i], u[32 + 8 * jj + i]});
        const int o = 8 * jj;
        hp[o] = pk(v[0].x, v[2].x); hp[o + 1] = pk(v[4].x, v[6].x); hp[o + 2] = pk(v[1].x, v[3].x); hp[o + 3] = pk(v[5].x, v[7].x);
        hp[o + 4] = pk(v[0].y, v[2].y); hp[o + 5] = pk(v[4].y, v[6].y); hp[o + 6] = pk(v[1].y, v[3].y); hp[o + 7] = pk(v[5].y, v[7].y);
        hp[o + jj] = (hp[o + jj] & hm) | hb;
        hp[o + 4 + jj] = (hp[o + 4 + jj] & hm) | hb;
        stg128(hptr + (jj >> 1) * 8192 + (jj & 1) * 512, hp[o], hp[o + 1], hp[o + 2], hp[o + 3]);
        stg128(hptr + 16384 + (jj >> 1) * 8192 + (jj & 1) * 512, hp[o + 4], hp[o + 5], hp[o + 6], hp[o + 7]);
        YIELD_S3();
        if (jj > 0) {
#pragma unroll
            for (int i = o - 8; i < o; i += 2) asm volatile("lop3.b32 %0, %0, %1, %2, 0x80;" : "+r"(keep) : "r"(hp[i]), "r"(hp[i + 1]));
        }
    }
}

__device__ __forceinline__ int pos_of(int n) { return (n & 24) + 4 * (n & 1) + ((n >> 1) & 3); }
__device__ __forceinline__ int unit_of(int role, int u, int& slot) {
    const int g = role & 7, w = (role >> 3) & 3, b = role >> 5;
    slot = role >= 128 ? g : (g ? 16 * g + w + 4 * b : 4 * w + b);
    return role >= 128 ? 32 * max(2 * g + u, 1) : (g ? g + 16 * w : ((w & 1) << 4) + ((w & 2) << 2)) + 64 * b + 256 * u;
}
template <int STRIDE> __device__ __forceinline__ bool tags_ok(uint32_t a, uint32_t ep) {
    uint32_t v[4], ok;
#pragma unroll
    for (int i = 0; i < 4; i++) {
        if (STRIDE || !i) asm volatile("ld.shared.u32 %0, [%1];" : "=r"(v[i]) : "r"(a + i * STRIDE) : "memory");
        else v[i] = v[0];
    }
    asm volatile("{.reg .pred p; .reg .b32 a, b; lop3.b32 a, %1, %2, %5, 0x7e; lop3.b32 b, %3, %4, %5, 0x7e; lop3.b32 a, a, b, 1, 0xa8;\n"
                 "setp.eq.u32 p, a, 0; vote.sync.all.pred p, p, -1; selp.u32 %0, 1, 0, p;}" : "=r"(ok) : "r"(v[0]), "r"(v[1]), "r"(v[2]), "r"(v[3]), "r"(ep));
    return ok;
}
__device__ __forceinline__ void load_w_rows(uint32_t dst, const CUtensorMap* mr, const CUtensorMap* mi, int kap, uint32_t bar) {
    mbar_expect_tx(bar, 16 * WPITCH);
#pragma unroll 1
    for (int i = 0; i < 2; i++, dst += 8 * WPITCH, kap = (512 - kap) & 511) {
        tma2d(dst, mr, (kap * 1026 >> 4) * 2, 0, bar);
        tma2d(dst + 4 * WPITCH, mi, (kap * 1026 >> 4) * 2, 0, bar);
    }
}
__device__ __forceinline__ void prefetch_w_rows(const CUtensorMap* mr, const CUtensorMap* mi, int kap) {
#pragma unroll 1
    for (int i = 0; i < 2; i++, kap = (512 - kap) & 511) {
        asm volatile("cp.async.bulk.prefetch.tensor.2d.L2.global [%0, {%1,%2}];" ::"l"(mr), "r"((kap * 1026 >> 4) * 2), "r"(0) : "memory");
        asm volatile("cp.async.bulk.prefetch.tensor.2d.L2.global [%0, {%1,%2}];" ::"l"(mi), "r"((kap * 1026 >> 4) * 2), "r"(0) : "memory");
    }
}
template <int K0, int K1> __device__ __forceinline__ void store_v(const uint32_t (&vo)[32], const uint8_t* vp, bool p) {
    if (p) {
#pragma unroll
        for (int k = K0; k < K1; k++)
            asm volatile("st.global.v2.b32 [%0], {%1,%2};" ::"l"(vp + (k >> 2) * (1 << 20) + ((k >> 1) & 1) * 8192 + (k & 1) * (4 * 32768)), "r"(vo[2 * k]), "r"(vo[2 * k + 1]) : "memory");
    }
}
__device__ __forceinline__ void hint_v(unsigned* cnt, int on) { asm volatile("{.reg .pred p; setp.ne.and.u32 p, %1, 0, p0; @p red.relaxed.gpu.global.add.u32 [%0], 1;}" ::"l"(cnt), "r"(on) : "memory"); }
#define SB0 1024
__device__ __forceinline__ uint64_t ring_desc(uint32_t sb, uint32_t off, uint32_t lbo, uint32_t swz) {
    uint64_t d;
    asm volatile("{.reg .b32 z; shr.u32 z, %1, 28; mov.b64 %0, {z, z}; add.u64 %0, %0, %2;}" : "=l"(d) : "r"(sb), "l"(mkdesc(SB0 + off, lbo, 1024, swz)));
    return d;
}
struct Ring {
    uint32_t full, rel;
    uint32_t n;
    bool sig;
};
__device__ __forceinline__ void ring_release(const Ring& r, uint32_t o) {
    if (r.sig) asm volatile("mbarrier.arrive.shared::cluster.b64 _, [%0];" ::"r"(r.rel + o) : "memory");
}
__device__ __forceinline__ void peek(uint32_t a, uint32_t ph) { asm volatile("mbarrier.test_wait.parity.shared::cta.b64 pk, [%0], %1;" ::"r"(a), "r"(ph) : "memory"); }
__device__ __forceinline__ void peek_wait(uint32_t a, uint32_t ph, uint32_t& n) {
    asm volatile("{@pk bra DONE;\n"
                 "LOOP: mbarrier.try_wait.parity.shared::cta.b64 pk, [%1], %2; add.u32 %0, %0, 1; setp.gt.or.u32 pk, %0, %3, pk; @!pk bra LOOP;\n"
                 "DONE: }" : "+r"(n) : "r"(a), "r"(ph), "n"(SPIN_LIMIT) : "memory");
}
#define SL(k) ((k) % NST)
#define PH(k) (((k) / NST) & 1)
#define HANDPOS 5
#define H64 "%64,%65,%66,%67,%68,%69,%70,%71,%72,%73,%74,%75,%76,%77,%78,%79,%80,%81,%82,%83,%84,%85,%86,%87,%88,%89,%90,%91,%92,%93,%94,%95," \
            "%96,%97,%98,%99,%100,%101,%102,%103,%104,%105,%106,%107,%108,%109,%110,%111,%112,%113,%114,%115,%116,%117,%118,%119,%120,%121,%122,%123,%124,%125,%126,%127"
#define WG_MMA "wgmma.mma_async.sync.aligned.m64n128k16.f32.bf16.bf16 "
#define DESC_B(S, j) "mov.b64 {t, hb}, %130; mov.b64 db, {%137 + 2048 * " #S " + 2 * " #j ", hb};\n"
#define MMA_LO(S, j, p) "add.u64 da, %129, 2048 * " #S " + %136 * " #j ";" DESC_B(S, j) WG_MMA "{" L64 "}, da, db, " #p ", 1, 1, %138, 0;\n"
#define MMA_HI(S, j, p) "add.u64 da, %129, 2048 * " #S " + 512 + %136 * " #j ";\n" WG_MMA "{" H64 "}, da, db, " #p ", 1, 1, %138, 0;\n"
#define X3(X)
#define X4(X)
#define X5(X) X
#define STEP(S, P, N, ph, pa, pr, X, Y) \
    "wgmma.fence.sync.aligned;\n" MMA_LO(S, 0, pa) MMA_HI(S, 0, pa) \
    "wgmma.commit_group.sync.aligned; wgmma.wait_group.sync.aligned 1; @" #pr " mbarrier.arrive.shared::cluster.b64 _, [%132 + 8 * " #P "];\n" MMA_LO(S, 1, 1) \
    "mbarrier.test_wait.parity.shared::cta.b64 pk, [%131 + 8 * " #N "], " #ph ";\n" X3(X) MMA_HI(S, 1, 1) X4(X) MMA_LO(S, 2, 1) X5(X) MMA_HI(S, 2, 1) MMA_LO(S, 3, 1) MMA_HI(S, 3, 1) \
    "wgmma.commit_group.sync.aligned;\n" P4A Y "@pk bra GO" #S ";\n" \
    "WAIT" #S ": mbarrier.try_wait.parity.shared::cta.b64 pk, [%131 + 8 * " #N "], " #ph "; add.u32 %128, %128, 1; setp.gt.or.u32 pk, %128, %139, pk; @!pk bra WAIT" #S ";\n" \
    "GO" #S ":\n" P4B
#define P4A
#define P4B
#define P4I
#define P4O
#define STEP_ARGS(TA) \
    : R8(d, 0), R8(d, 8), R8(d, 16), R8(d, 24), R8(d, 32), R8(d, 40), R8(d, 48), R8(d, 56), \
      R8(d, 64), R8(d, 72), R8(d, 80), R8(d, 88), R8(d, 96), R8(d, 104), R8(d, 112), R8(d, 120), "+r"(r.n) \
    : "l"(ha), "l"(hb), "r"(r.full), "r"(r.rel), "r"((uint32_t)r.sig), "r"(wg), \
      "n"(SB0 / 16 + (TA ? 32 << 16 : 1 << 16)), "n"(TA ? 128 : 2), "n"(SB0 / 16 + 1024 + (1 << 16)), "n"(TA), "n"(SPIN_LIMIT) P4O \
    : "memory"
#define STEP_REGS "{.reg .b32 k, t, ph, hb; .reg .b64 da, db; .reg .pred ps, pl, pa, pr;\n" P4I "setp.ne.u32 ps, %133, 0;\n"
#define FIRST_WAIT "FIRST: mbarrier.try_wait.parity.shared::cta.b64 pk, [t], ph; @pk bra START; add.u32 %128, %128, 1; setp.le.u32 pk, %128, %139; @pk bra FIRST; START:\n"
__device__ __forceinline__ void gemm1(float (&d)[128], Ring& r, uint64_t ha, uint64_t hb, int wg) {
    asm volatile(STEP_REGS "mul.lo.u32 k, %134, 15; mov.b32 ph, %134; setp.ne.u32 pl, k, 0; mad.lo.u32 t, %134, 8, %131;\n"
                 "pmevent 1; @pl bar.sync 1, 256;\n" FIRST_WAIT "@pl bra ONE;\n"
                 "LOOP: setp.ne.u32 pa, k, 0; and.pred pr, pa, ps; setp.eq.u32 pl, k, 15;\n"
                 STEP(0, 4, 1, ph, pa, pr, "@pl bar.arrive 1, 256;\n", "@pl bra END;\n")
                 "ONE: setp.ne.u32 pa, k, 15; and.pred pr, pa, ps; setp.eq.u32 pl, k, 30;\n"
                 STEP(1, 0, 2, ph, pa, pr, "@pl bar.arrive 2, 256;\n", "@pl bra END;\n")
                 STEP(2, 1, 3, ph, 1, ps, "", "") STEP(3, 2, 4, ph, 1, ps, "", "") "xor.b32 ph, ph, 1; add.u32 k, k, 5;\n" STEP(4, 3, 0, ph, 1, ps, "", "")
                 "bra LOOP;\n"
                 "END:\n" P4B "}" STEP_ARGS(0));
}
__device__ __forceinline__ void gemm2(float (&d)[128], Ring& r, uint64_t ha, uint64_t hb, int wg) {
    asm volatile(STEP_REGS "mov.b32 k, 0; mov.b32 ph, 0; add.u32 t, %131, 16;\n"
                 "pmevent 1; bar.sync 2, 256;\n" FIRST_WAIT
                 "LOOP: setp.ne.u32 pa, k, 0; and.pred pr, pa, ps; setp.eq.u32 pl, k, 5;\n"
                 STEP(2, 1, 3, ph, pa, pr, "", "") STEP(3, 2, 4, ph, 1, ps, "", "") "xor.b32 ph, ph, 1; add.u32 k, k, 1;\n" STEP(4, 3, 0, ph, 1, ps, "", "")
                 "@pl bra END;\n" STEP(0, 4, 1, ph, 1, ps, "", "") STEP(1, 0, 2, ph, 1, ps, "", "")
                 "bra LOOP;\n"
                 "END: }" STEP_ARGS(1));
}
template <int O, int K, int J> __device__ __forceinline__ void mma_h(float (&y)[128], uint64_t a, uint64_t b) { mma128_ss<O, 1, 0>(y, a + SL(K) * 2048 + O * 8 + 128 * J, b + SL(K) * 2048 + 2 * J, 1); }
template <int O, int K> __device__ __forceinline__ void half_step(float (&y)[128], uint64_t a, uint64_t b) { mma_h<O, K, 0>(y, a, b); mma_h<O, K, 1>(y, a, b); mma_h<O, K, 2>(y, a, b); mma_h<O, K, 3>(y, a, b); }
template <int R, int U> __device__ __forceinline__ void out_piece(float (&y)[128], const uint32_t (&dd)[16], uint32_t x0, uint32_t x1, float* op) {
    const int i = 64 * (R >> 1) + 8 * U + 2 * (R & 1);
    asm("mul.rn.bf16x2 %0, %0, %1;" : "+r"(x0) : "r"(dd[2 * U]));
    asm("mul.rn.bf16x2 %0, %0, %1;" : "+r"(x1) : "r"(dd[2 * U + 1]));
    asm volatile("st.global.v4.f32 [%0], {%1,%2,%3,%4};" ::"l"(op + (32 * (R & 1) + 16 * (R >> 1)) * 2048 + 16 * U),
                 "f"(y[i] + __uint_as_float(x0 << 16)), "f"(y[i + 1] + __uint_as_float(x0 & 0xffff0000u)),
                 "f"(y[i + 4] + __uint_as_float(x1 << 16)), "f"(y[i + 5] + __uint_as_float(x1 & 0xffff0000u)) : "memory");
}
template <int R, int U0> __device__ __forceinline__ void load_x4(uint32_t (&xx)[8], uint32_t xa) {
#pragma unroll
    for (int u = 0; u < 4; u++)
        asm volatile("ld.shared.v2.b32 {%0,%1}, [%2];" : "=r"(xx[2 * u]), "=r"(xx[2 * u + 1]) : "r"((xa ^ (u << 5)) + (3 - R) * 8192 + U0 * 1024) : "memory");
}
__device__ __forceinline__ Ring ring_at(uint32_t sb, int k) {
    Ring r;
    r.n = 0;
    r.full = sb + OFF_BAR + B_FULL;
    asm("mapa.shared::cluster.u32 %0, %1, %2;" : "=r"(r.rel) : "r"(sb + OFF_BAR + B_EMPTY), "r"((threadIdx.x >> 5) & 1));
    r.sig = __shfl_sync(~0u, threadIdx.x & 95, threadIdx.x) == 0;
    return r;
}

template <bool BY_SM> __global__ void __cluster_dims__(2, 1, 1) __launch_bounds__(512, 1)
fused_kernel(const __grid_constant__ CUtensorMap tmX, const __grid_constant__ CUtensorMap tmBre, const __grid_constant__ CUtensorMap tmBim,
             const __grid_constant__ CUtensorMap tmCre, const __grid_constant__ CUtensorMap tmCim, const __grid_constant__ CUtensorMap tmXd,
             const __grid_constant__ CUtensorMap tmUst,
             const __grid_constant__ CUtensorMap tmWr, const __grid_constant__ CUtensorMap tmWi, const __grid_constant__ CUtensorMap tmXa,
             const Params p) {
    extern __shared__ __align__(1024) uint8_t smraw[];
    asm volatile(".reg .pred pk, p0;");
    const int tid = TIDMAP, rank = blockIdx.x & 1;
    const uint32_t wi = __shfl_sync(~0u, smem_u32(smraw) + (tid >> 5), 0), sb = wi & ~15u, bars = sb + OFF_BAR;
    const int wg = (wi >> 2) & 3, w = wi & 3, lane = tid & 31, g = lane >> 2, q = lane & 3;
    if (wg != 3) asm volatile("barrier.cluster.arrive.relaxed.aligned; barrier.cluster.wait.aligned;" ::: "memory");
    else asm volatile("prefetch.tensormap [%0];" ::"l"(w == 0 ? &tmX : w == 1 ? &tmBre : &tmBim) : "memory");
    int role;
    {
        uint32_t T = blockIdx.x;
        if (BY_SM) asm("mov.u32 %0, %%smid;" : "=r"(T));
        T >>= 1;
        const uint32_t a = ((T - 32) * 37) >> 8;
        asm("{.reg .pred p; setp.lt.u32 p, %1, 62; selp.u32 %0, 4, -58, p; add.u32 %0, %0, %1;\n"
            "setp.lt.u32 p, %1, 60; selp.u32 %0, %2, %0, p; setp.lt.u32 p, %1, 32; selp.u32 %0, %3, %0, p;}"
            : "=&r"(role) : "r"(T), "r"(8 * (T - 31 - 7 * a) + 4 + a), "r"(8 * (T & 7) + (T >> 3)));
        role = 2 * role + rank;
    }
    const bool spare = role >= 128;
    const int tc = ((role >> 3) & 14) + rank, cb = (role >> 1) & 7;
    const int fb = role >> 5, fcb = role & 31, fpos = pos_of(fcb);
    const int nu = role == 128 ? 1 : (fcb || !role ? 2 : 0);

    if (wg == 3) {
        if (elect_one()) {
            const uint32_t b = bars + w * 8;
            STAMP5(57);
            mbar_init(b, 1);
            if (w < XW && !spare) {
                mbar_expect_tx(b, 32768);
                tma5d(sb + w * 32768 + 16384, &tmX, w * 64, 0, 0, 0, tc, b);
                if (w == 0) { tma4d(sb, &tmBre, 0, 0, 0, cb * 4, b); tma4d(sb + 8192, &tmBim, 0, 0, 0, cb * 4, b); }
                STAMP5(58);
            }
#pragma unroll
            for (int o = 32; o < B_EPOCH; o += 32) mbar_init(b + o, o < B_EMPTY ? 1 : (o < B_STG ? 2 : (o < B_P3M ? 4 : 8)));
            asm volatile("fence.mbarrier_init.release.cluster;" ::: "memory");
        }
        __syncwarp();
        STAMP5(59);
        asm volatile("barrier.cluster.arrive.relaxed.aligned;" ::: "memory");
    }
    if (opaque32(wg) == 3) {
        asm volatile("setmaxnreg.dec.sync.aligned.u32 24;");
        asm volatile("barrier.cluster.wait.aligned;" ::: "memory");
        if (w == 0) {
            if (!spare && elect_one()) {
                STAMP(56);
#pragma unroll 1
                for (int k = 1; k < NST; k++) {
                    if (k >= XW) mbar_expect_tx(bars + B_FULL + k * 8, 32768);
                    tma4d_mc(sb + k * 32768 + rank * 8192, rank ? &tmBim : &tmBre, k * 64, 0, 0, cb * 4, bars + B_FULL + k * 8);
                    if (k >= XW) tma5d(sb + k * 32768 + 16384, &tmX, k * 64, 0, 0, 0, tc, bars + B_FULL + k * 8);
                }
#define RING_WAIT "mbarrier.try_wait.parity.shared::cta.b64 p, [fb + 256], ph; @p bra GO;\n" \
                  "WAIT: mbarrier.try_wait.parity.shared::cta.b64 p, [fb + 256], ph; add.u32 n, n, 1; setp.gt.or.u32 p, n, 32768, p; @!p bra WAIT;\nGO:\n"
#define RING_NEXT "pmevent 1; add.u32 o, o, 8; setp.eq.u32 p, o, 40; selp.u32 o, 0, o, p; @p xor.b32 ph, ph, 1; add.u32 fb, %1, o; shl.b32 t, o, 12; add.u32 da, %0, t;\n"
                asm volatile("{.reg .b32 o, k, kk, c2, da, db, fb, ph, n, t; .reg .pred p;\n"
                             "mov.b32 o, 0; mov.b32 k, 320; mov.b32 kk, 320; mov.b32 c2, 0; mov.b32 ph, 0; mov.b32 n, 0; mov.b32 fb, %1; mov.b32 da, %0; mov.b32 db, %2;\n"
                             "LOOP:\n" RING_WAIT
                             "cp.async.bulk.tensor.5d.shared::cluster.global.mbarrier::complete_tx::bytes [da], [%3, {kk,0,0,0,%5}], [fb];\n"
                             "cp.async.bulk.tensor.4d.shared::cluster.global.mbarrier::complete_tx::bytes.multicast::cluster [db], [%4, {kk,0,c2,%6}], [fb], %7;\n"
                             "mbarrier.arrive.expect_tx.shared::cta.b64 _, [fb], 32768;\n" RING_NEXT
                             "add.u32 db, %2, t; add.u32 k, k, 64; and.b32 kk, k, 1023; shr.u32 c2, k, 9; and.b32 c2, c2, 2; setp.ne.u32 p, k, 2048; @p bra LOOP;}"
                             ::"r"(sb + 16384), "r"(bars + B_FULL), "r"(sb + rank * 8192), "l"(&tmX), "l"(rank ? &tmBim : &tmBre), "r"(tc), "r"(cb * 4), "h"((uint16_t)3) : "memory");
                asm volatile("{.reg .b32 o, k, kk, da, db, fb, hb, ph, n, t; .reg .b64 m, src; .reg .pred p;\n"
                             "mov.b32 o, 16; mov.b32 k, 0; mov.b32 kk, 0; mov.b32 ph, 1; mov.b32 n, 0; add.u32 fb, %1, 16; add.u32 hb, %1, 72; add.u32 da, %0, 65536; add.u32 db, %2, 65536;\n"
                             "mov.b64 m, %3; mov.b64 src, %5;\n"
                             "GROUP: add.u32 t, %8, k;\n"
                             "OWN: mbarrier.try_wait.parity.shared::cta.b64 p, [t], 0; add.u32 n, n, 1; setp.gt.or.u32 p, n, 32768, p; @!p bra OWN;\n"
                             "LOOP:\n" RING_WAIT
                             "cp.async.bulk.shared::cluster.global.mbarrier::complete_tx::bytes [da], [src], 16384, [hb];\n"
                             "cp.async.bulk.tensor.5d.shared::cluster.global.mbarrier::complete_tx::bytes.multicast::cluster [db], [m, {kk,0,0,0,%6}], [fb], %7;\n"
                             "mbarrier.expect_tx.shared::cta.b64 [fb], 16384; mbarrier.arrive.expect_tx.shared::cta.b64 _, [hb], 16384;\n" RING_NEXT
                             "add.u32 db, %2, t; add.u64 src, src, 16384; sub.u64 m, %4, m; add.u32 k, k, 1; shl.b32 kk, k, 5; and.b32 kk, kk, 0x7c0;\n"
                             "and.b32 t, k, 1; mad.lo.u32 hb, t, 8, fb; add.u32 hb, hb, o; add.u32 hb, hb, 40;\n"
                             "and.b32 t, k, 7; setp.ne.u32 p, t, 0; @p bra LOOP; setp.ne.u32 p, k, 32; @p bra GROUP;}"
                             ::"r"(sb), "r"(bars + B_FULL), "r"(sb + 16384 + rank * 8192), "l"(&tmCre), "l"((uint64_t)&tmCre + (uint64_t)&tmCim),
                               "l"(g_H + (size_t)tc * 32 * 16384), "r"(cb * 8 + rank * 4), "h"((uint16_t)3), "r"(bars + B_HOWN) : "memory");
            }
        } else if (opaque32(w) == 1) {
            const unsigned ep = ld_rlx(g_epoch + role * 8) + 1;
            __syncwarp();
            if (elect_one()) {
                asm volatile("st.relaxed.gpu.global.u32 [%0], %1;" ::"l"(g_epoch + role * 8), "r"(ep) : "memory");
                asm volatile("st.shared.u32 [%0], %1;" ::"r"(bars + B_EPOCH), "r"(ep) : "memory");
                mbar_arrive(bars + B_EP);
            }
            int slot;
            const int kap = unit_of(role, 0, slot), kap1 = unit_of(role, 1, slot);
            uint32_t lph = 0;
            if (!spare) mbar_wait(bars + B_STGU, 0);
            STAMP(21);
            const int c0 = fb * 2048 + fpos * 64;
            if (elect_one()) {
                if (!spare) {
#pragma unroll 1
                    for (int r = 4; r < 8; r++) bulk_st(g_X + r * (32 * 16384) + c0 * 2, sb + OFF_P + r * 4096, 128);
                    tma2d_st(&tmUst, c0, 0, sb + OFF_P);
                    bulk_commit();
                    tma2d_st(&tmUst, c0, 64, sb + OFF_P + 8192);
                    bulk_commit();
                    if (UHINT == 1) asm volatile("cp.async.bulk.wait_group.read 1;" ::: "memory");
                    if (UHINT < 2) red_hint(g_cnt);
                }
                mbar_expect_tx(bars + B_FG, 8192);
                bulk_ld(sb + OFF_F, (const uint8_t*)g_tab + TAB_FG, 8192, bars + B_FG);
            }
            STAMP(40);
#pragma unroll 1
            for (int e = 0; e < 4; e++) {
                if (e >= 2) {
                    if (e == nu) {
                        mbar_wait(bars + B_WFREE, 0);
                        if (elect_one()) load_w_rows(sb + OFF_WD, &tmWr, &tmWi, kap1, bars + B_WD);
                    }
                    if (e - 2 < nu) mbar_wait(bars + B_STG, e & 1);
                    STAMPO(23, e - 2);
                    if (e == 3 && !spare && elect_one()) {
                        mbar_expect_tx(bars + B_FG, 8192);
                        bulk_ld(sb + OFF_F, (const uint8_t*)g_tab + TAB_G + fb * 8192, 8192, bars + B_FG);
                    }
                }
                const uint32_t tg = e < 2 ? lane * 128 + ((((lane >> 1) & 2) ^ (lane & 3)) << 4) + (lane >> 3) * 4 : lane * 64 + (lane & 8) * 4 + (lane & 2) * 8 + (lane & 4) * 2;
                if (spare) {
                    if (e == 1) {
                        wait_cnt(g_cnt, 128 * ep);
                        STAMP(42);
#pragma unroll 1
                        for (int n = 0; n < 4096; n++) {
                            if (elect_one()) {
                                mbar_expect_tx(bars + B_LD, 8 * 16384);
#pragma unroll 1
                                for (int r = 0; r < 8; r++) bulk_ld(sb + r * 16384, g_X + (size_t)r * (32 * 16384), 16384, bars + B_LD);
                            }
                            mbar_wait(bars + B_LD, n & 1);
                            bool ok = true;
#pragma unroll 1
                            for (int r = 0; r < 8; r++) ok &= tags_ok<4096>(sb + r * 16384 + tg, ep);
                            if (ok) break;
                        }
                        if (elect_one()) mbar_arrive(bars + B_RAW);
                    }
                } else {
                    const uint32_t dst = sb + OFF_P + (e & 1) * 16384;
                    wait_cnt(g_cnt + e * 32, 128 * ep);
                    STAMPO(41, e == 2 ? -12 : e);
#pragma unroll 1
                    for (int n = 0; n < 4096; n++) {
                        if (elect_one()) {
                            bulk_wait_read();
                            mbar_expect_tx(bars + B_LD, 16384);
                            bulk_ld(dst, g_X + (size_t)(e < 2 ? role + e * 128 : 254 + (fb * 32 + fpos) * 2 + e) * 16384, 16384, bars + B_LD);
                            if (U1POS <= 0 && e + n == 0) {
                                if (U1POS < 0 && nu) load_w_rows(sb + OFF_WD, &tmWr, &tmWi, kap, bars + B_WD);
                                tma2d_st(&tmUst, c0, 128, dst + 16384); tma2d_st(&tmUst, c0, 192, dst + 24576); bulk_commit();
                                if (U1POS == -2) { bulk_wait_read(); red_hint(g_cnt + 32); }
                            }
                        }
                        mbar_wait(bars + B_LD, lph);
                        if (!e) STAMP3(49);
                        lph ^= 1;
                        if (tags_ok<4096>(dst + tg, ep) & tags_ok<4096>(dst + tg + (e & 2) * 1024, ep) & tags_ok<0>(dst + (e == 3 ? (lane & 1) * 8192 + 32 : 0), ep)) break;
                    }
                    if (elect_one()) mbar_arrive(bars + B_IN + e * 8);
                }
                if (e < 2 && elect_one()) {
                    if (e) prefetch_w_rows(&tmWr, &tmWi, kap1);
                    else {
                        if (U1POS < 0 ? spare : nu) load_w_rows(sb + OFF_WD, &tmWr, &tmWi, kap, bars + B_WD);
                        if (!spare && U1POS != -2) {
                            if (U1POS > 0) { tma2d_st(&tmUst, c0, 128, sb + OFF_P + 16384); bulk_commit(); tma2d_st(&tmUst, c0, 192, sb + OFF_P + 24576); bulk_commit(); }
                            if (U1POS == 2) asm volatile("cp.async.bulk.wait_group.read 1;" ::: "memory"); else bulk_wait_read();
                            red_hint(g_cnt + 32);
                        }
                    }
                }
            }
            if (!spare) {
                mbar_wait(bars + B_HOWN + 8, 0);
#pragma unroll 1
                for (int r = 0; r < 4; r++) {
                    if (r == 3) mbar_wait(bars + B_P3M, 0);
                    if (elect_one()) {
                        if (r == 0) { mbar_expect_tx(bars + B_XD, 24576 + 256); mbar_expect_tx(bars + B_XD + 8, 8192); bulk_ld(sb + OFF_LAM, p.dsk + cb * 128, 256, bars + B_XD); }
                        tma4d(sb + OFF_F + (3 - r) * 8192, &tmXd, 0, tc * 128 + 32 * (r & 1) + 16 * (r >> 1), 0, cb * 2, bars + B_XD + (r == 3) * 8);
                    }
                    __nanosleep(PACE_X);
                }
            }
        } else {
            if (w == 2) {
                {
                    const int u = lane >> 4;
                    int slot;
                    const int r0 = unit_of(role, u, slot) + 512 * ((lane >> 1) & 3), r1 = (2048 - r0) & 2047, mir = (lane >> 3) & 1;
                    const unsigned short* wp = (const unsigned short*)((lane & 1) ? p.wi : p.wr);
                    const float a = bf2f(wp[r0 * 513 + mir * 512]), b = bf2f(wp[r1 * 513 + mir * 512]);
                    asm volatile("st.shared.f32 [%0], %1;" ::"r"(sb + OFF_WSP + u * 64 + (lane & 15) * 4), "f"(0.5f * ((lane & 1) ? (mir ? b - a : a - b) : a + b)) : "memory");
                }
                warp_arrive(bars + B_WSP);
            } else if (!spare) {
                if (XA_T0) __nanosleep(XA_T0);
#pragma unroll 1
                for (int i = 0; i < 8; i++) {
                    if (i >= XA_N0) __nanosleep(XA_PACE);
                    if (elect_one()) {
                        const uint32_t xb = bars + (P1H && i < 4 ? B_RAW : B_XIN);
                        if (P1H ? !(i & 3) : !i) mbar_expect_tx(xb, P1H ? 16384 : 32768);
                        tma3d(sb + OFF_F + i * 4096, &tmXa, fcb * 32, 0, 4 * i + fb, xb);
                    }
                }
            }
            if (!spare) {
                if (w == 2 && nu) {
                    int slot;
                    const int kap = unit_of(role, 0, slot);
                    mbar_wait(bars + WPFB, 0);
                    if (elect_one()) prefetch_w_rows(&tmWr, &tmWi, kap);
                }
                const unsigned ep = get_epoch(bars);
#define CNT_RETRY
#define CNT_ARG
                asm volatile("{.reg .b32 o, k, hb, fb, ca, m, ph, rph, n, t, v0, v1, v2, v3; .reg .b64 src; .reg .pred p, pe;\n"
                             "elect.sync _|pe, 0xffffffff; mov.b32 o, %0; shr.u32 k, %0, 3; sub.u32 k, k, 2; mov.b32 m, 0x107c0; mov.b32 rph, 0; mov.b32 n, 0;\n"
                             "bra NEXT;\n"
                             "LOOP: mbarrier.try_wait.parity.shared::cta.b64 p, [hb], ph; @p bra GO;\n"
                             "WAIT: mbarrier.try_wait.parity.shared::cta.b64 p, [hb], ph; add.u32 n, n, 1; setp.gt.or.u32 p, n, 32768, p; @!p bra WAIT;\n"
                             "GO: ld.shared.u32 v0, [ca]; ld.shared.u32 v1, [ca + 128]; ld.shared.u32 v2, [ca + 256]; ld.shared.u32 v3, [ca + 384];\n"
                             "lop3.b32 v0, v0, v1, %4, 0x7e; lop3.b32 v2, v2, v3, %4, 0x7e; lop3.b32 v0, v0, v2, 1, 0xa8; setp.eq.u32 p, v0, 0; vote.sync.all.pred p, p, -1; @p bra OK;\n"
                             CNT_RETRY "add.u32 n, n, 16; setp.gt.u32 p, n, 32768; @p bra OK;\n"
                             "shl.b32 t, o, 12; add.u32 t, t, %5; mad.wide.u32 src, k, 16384, %6;\n"
                             "@pe mbarrier.arrive.expect_tx.shared::cta.b64 _, [%7], 16384; @pe cp.async.bulk.shared::cluster.global.mbarrier::complete_tx::bytes [t], [src], 16384, [%7];\n"
                             "AGAIN: mbarrier.try_wait.parity.shared::cta.b64 p, [%7], rph; add.u32 n, n, 1; setp.gt.or.u32 p, n, 32768, p; @!p bra AGAIN;\n"
                             "xor.b32 rph, rph, 1; bra GO;\n"
                             "OK: @pe mbarrier.arrive.shared::cta.b64 _, [fb]; pmevent 1;\n"
                             "add.u32 o, o, 16; setp.ge.u32 p, o, 40; @p sub.u32 o, o, 40; add.u32 k, k, 2;\n"
                             "NEXT: shr.u32 m, m, 1; and.b32 ph, m, 1; add.u32 fb, %1, o; mad.lo.u32 hb, o, 2, %2; mad.lo.u32 ca, o, 4096, %3; setp.lt.u32 p, k, 32; @p bra LOOP;}"
                             ::"r"(8 * w), "r"(bars + B_FULL), "r"(bars + B_HL - 16 + w * 8), "r"(sb + (q >> 1) * 8192 + (q & 1) * 512 + g * 1040 + q * 4), "r"(ep),
                               "r"(sb), "l"(g_H + (size_t)tc * 32 * 16384), "r"(bars + B_HR - 16 + w * 8) CNT_ARG : "memory");
                if (w == 3) warp_arrive(bars + B_DONE);
            }
        }
    } else {
        STAMP(55);
        asm volatile("setmaxnreg.inc.sync.aligned.u32 152;");
        STAMP5(60);
        const int t7 = tid & 127, hf = wg - 1;
        const int mi = lane >> 3, gl = lane & 7;
        if (spare && wg != 2) {
            if (tid < 64) { const uint4 v = __ldg((const uint4*)((const uint8_t*)g_tab + TAB_PC) + tid); sts128(sb + OFF_LAM + tid * 16, v.x, v.y, v.z, v.w); }
            bar_sync(1, 256);
            mbar_wait(bars + B_RAW, 0);
            STAMP(0);
#pragma unroll 1
            for (int u = 0; u < nu; u++) {
                int slot;
                const int t = unit_of(role, u, slot) >> 5;
                const uint32_t off = (tid >> 2) * 128 + q * 16;
                float zr[16], zi[16];
#pragma unroll
                for (int k = 0; k < 16; k++) zr[k] = zi[k] = 0.f;
#pragma unroll 1
                for (int r = (t & 1) ? 0 : t >> 1; r < 8 - ((t & 1) ? 0 : (t >> 1) - 1); r += (t & 1) ? 1 : 8 - t) {
                    float4 c;
                    float a[8], b[8];
                    lds128f(sb + OFF_LAM + t * 128 + r * 16, c.x, c.y, c.z, c.w);
                    lds128f(sb + r * 16384 + off, a[0], a[1], a[2], a[3]);
                    lds128f(sb + r * 16384 + off + 64, b[0], b[1], b[2], b[3]);
                    lds128f(sb + r * 16384 + off + 8192, a[4], a[5], a[6], a[7]);
                    lds128f(sb + r * 16384 + off + 8192 + 64, b[4], b[5], b[6], b[7]);
#pragma unroll
                    for (int k = 0; k < 16; k++) {
                        const uint32_t ua = __float_as_uint(a[k >> 1]), ub = __float_as_uint(b[k >> 1]);
                        const float x = __uint_as_float((k & 1) ? ua & 0xffff0000u : ua << 16), y = __uint_as_float((k & 1) ? ub & 0xffff0000u : ub << 16);
                        zr[k] = fmaf(c.x, x, fmaf(c.z, y, zr[k]));
                        zi[k] = fmaf(c.y, x, fmaf(c.w, y, zi[k]));
                    }
                }
                const uint32_t dst = sb + OFF_P + u * 16384 + off;
#pragma unroll
                for (int k = 0; k < 16; k += 8) {
                    sts128(dst + k * 1024, pk(zr[k], zr[k + 1]), pk(zr[k + 2], zr[k + 3]), pk(zr[k + 4], zr[k + 5]), pk(zr[k + 6], zr[k + 7]));
                    sts128(dst + k * 1024 + 64, pk(zi[k], zi[k + 1]), pk(zi[k + 2], zi[k + 3]), pk(zi[k + 4], zi[k + 5]), pk(zi[k + 6], zi[k + 7]));
                }
                fence_async_sm();
                bar_sync(1, 256);
                if (tid == 0) mbar_arrive(bars + B_IN + u * 8);
                STAMPO(1, u);
            }
            return;
        }
        if (wg == 2 && !spare) {
            asm volatile("setmaxnreg.inc.sync.aligned.u32 176;");
            uint32_t f1[16];
            cf tw[8];
            if (TAB_T0) __nanosleep(TAB_T0);
            ldtab<4, 2048>(f1, TAB_F1 + t7 * 16);
            ldtab_cf<16>(tw, TAB_TW1 + (t7 >> 2) * 64);
            const uint32_t ep = get_epoch(bars);
            uint32_t a0 = sb + OFF_P + (8 * w + gl + 32 * (mi >> 1)) * 128 + (((((mi & 1) << 2) | (fpos & 3)) ^ gl) << 4);
            float acc[128];
            const uint64_t dx = opaque(mkdesc(sb + OFF_F, 4096, 512, 2));
            mbar_wait(bars + (P1H ? B_RAW : B_XIN), 0);
            pinu(f1);
            wg_fence();
#pragma unroll
            for (int j = 0; j < 4; j++) mma128_rs<0, 1>(acc, f1[4 * j], f1[4 * j + 1], f1[4 * j + 2], f1[4 * j + 3], dx + j * 64, j);
            if (P1H) { wg_commit(); mbar_wait(bars + B_XIN, 0); wg_fence(); }
            STAMP(20);
#pragma unroll
            for (int j = 0; j < 4; j++) mma128_rs<64, 1>(acc, f1[4 * j], f1[4 * j + 1], f1[4 * j + 2], f1[4 * j + 3], dx + 1024 + j * 64, j);
            wg_commit();
            wg_wait<0>();
            pin(acc);
            pinu(f1);
#pragma unroll 1
            for (int h = 0;; h++) {
                const uint32_t tmask = 2 * q + h == fpos >> 2 ? ~1u : ~0u, tbit = ep & ~tmask;
#pragma unroll
                for (int cl = 0; cl < 2; cl++) {
                    c2 v[8];
#pragma unroll
                    for (int n = 0; n < 8; n++) {
                        const int i = 4 * (4 * n + cl);
                        v[n] = {{acc[i], acc[i + 2]}, {acc[i + 1], acc[i + 3]}};
                    }
                    dft8<true, YP1>(v, tw);
#pragma unroll
                    for (int r = 0; r < 8; r += 2) {
                        uint32_t o0 = pk(v[r].a.x, v[r].b.x), o1 = pk(v[r].a.y, v[r].b.y), o2 = pk(v[r + 1].a.x, v[r + 1].b.x), o3 = pk(v[r + 1].a.y, v[r + 1].b.y);
                        if (cl == 0) { o0 = (o0 & tmask) | tbit; o2 = (o2 & tmask) | tbit; }
                        stsm4((a0 ^ (cl << 4)) + r * 4096, o0, o1, o2, o3);
                    }
                }
                if (h) break;
                a0 ^= 32;
#pragma unroll
                for (int n = 0; n < 8; n++) {
                    asm volatile("mov.b32 %0, %8; mov.b32 %1, %9; mov.b32 %2, %10; mov.b32 %3, %11; mov.b32 %4, %12; mov.b32 %5, %13; mov.b32 %6, %14; mov.b32 %7, %15; pmevent 1;"
                                 : "=&f"(acc[16 * n]), "=&f"(acc[16 * n + 1]), "=&f"(acc[16 * n + 2]), "=&f"(acc[16 * n + 3]), "=&f"(acc[16 * n + 4]), "=&f"(acc[16 * n + 5]), "=&f"(acc[16 * n + 6]), "=&f"(acc[16 * n + 7])
                                 : "f"(acc[16 * n + 8]), "f"(acc[16 * n + 9]), "f"(acc[16 * n + 10]), "f"(acc[16 * n + 11]), "f"(acc[16 * n + 12]), "f"(acc[16 * n + 13]), "f"(acc[16 * n + 14]), "f"(acc[16 * n + 15]));
                }
            }
            fence_async_sm();
            warp_arrive(bars + B_STGU);
            bar_sync(3, 128);
            asm volatile("setmaxnreg.dec.sync.aligned.u32 152;");
            bar_arrive(7, 256);
        }
        if (wg == 1) {
            if (LAM_T0) __nanosleep(LAM_T0);
            const int cl = tid & 127, ch = (cl >> 6) * 512 + ((cl >> 3) & 1) * 256 + cb * 32 + ((cl >> 4) & 3) * 8 + (cl & 7);
            const float lr = bf2f(*(const unsigned short*)padd(p.lre, 2 * ch)), li = bf2f(*(const unsigned short*)padd(p.lim, 2 * ch));
            const float dt = __bfloat162float(__float2bfloat16(expf(bf2f(*(const unsigned short*)padd(p.ldt, 2 * ch)))));
            const float an = dt * li, th = an * 0.318309873342514f;
            float sn, cs, inv;
            sincospif(fmaf(rintf(0.5f * th), -2.f, th) + fmaf(an, 1.2841276653e-8f, fmaf(an, 0.318309873342514f, -th)), &sn, &cs);
            const float ex = expf(dt * lr), br = ex * cs, bi = ex * sn;
            asm("rcp.approx.f32 %0, %1;" : "=f"(inv) : "f"(lr * lr + li * li));
            inv += inv;
            const float cr = ((br - 1.f) * lr + bi * li) * inv, ci = (bi * lr - (br - 1.f) * li) * inv;
            sts128(sb + OFF_LAM + cl * 16, __float_as_uint(br), __float_as_uint(-bi), __float_as_uint(cr), __float_as_uint(-ci));
            mbar_wait(bars + B_EP, 0);
            bar_sync(8, 128);
            if (tid == 128) mbar_arrive(bars + B_LAM);
        }
        if (wg != 2) {
        if (wg == 0) bar_sync(4, 128); else bar_sync(7, 256);
        asm volatile("setmaxnreg.inc.sync.aligned.u32 160;");
        if (wg == 0) bar_sync(4, 128);
        float d[128];
        STAMPW(0, 10);
        Ring rg = ring_at(sb, role * 66 + wg * 16);
        cf lam[2];
        unsigned ep;
        gemm1(d, rg, ring_desc(sb, 0, 16, 1), ring_desc(sb, 16384, 16, 1), wg);
        const uint32_t lama = sb + OFF_LAM + wg * 1024 + w * 256 + (fresh_lane() & 28) * 4;
        mbar_wait_fast(bars + B_LAM, 0);
        lam[0] = lds_cf(lama); lam[1] = lds_cf(lama + 128);
        asm volatile("ld.shared.u32 %0, [%1];" : "=r"(ep) : "r"(bars + B_EPOCH) : "memory");
        asm volatile("setmaxnreg.inc.sync.aligned.u32 176;");
        cf L[2] = {lam[0], lam[1]};
#pragma unroll
        for (int i = 0; i < 4; i++) { L[0] = csq(L[0]); L[1] = csq(L[1]); }
        asm volatile("" : "+f"(L[0].x), "+f"(L[0].y), "+f"(L[1].x), "+f"(L[1].y)::"memory");
        wg_wait<0>();
        ring_release(rg, 8 * wg);
        pin(d);
        STAMPW(1, 11);
        {
            const int lane = fresh_lane(), g = lane >> 2, q = lane & 3, mi = lane >> 3, gl = lane & 7;
            cf f[2], fb2[2];
#pragma unroll
            for (int i = 0; i < 17; i++) {
#pragma unroll
                for (int h = 0; h < 2; h++) {
                    const int r = 4 * (i >> 1) + 2 * h + (i & 1), r2 = 32 + 4 * ((i - 1) >> 1) + 2 * h + ((i - 1) & 1);
                    if (i < 16) f[h] = i ? cfma(lam[h], f[h], {d[r], -d[64 + r]}) : cf{d[r], -d[64 + r]};
                    if (i > 0) fb2[h] = i > 1 ? cfma(lam[h], fb2[h], {d[r2], -d[64 + r2]}) : cf{d[r2], -d[64 + r2]};
                    if (i && (h || !(YS & 8))) YIELD_S1();
                }
            }
            const uint8_t* cbase = (const uint8_t*)g_carry + (tc * 16 + wg * 8 + cb) * 512 + w * 64;
            const uint8_t* cptr = padd(cbase, g * 8);
            const unsigned tag = ep & 15u;
#pragma unroll
            for (int h = 0; h < 2; h++) { f[h] = cfma(L[h], f[h], fb2[h]); L[h] = csq(L[h]); }
            cf s0[2], s1[2], s2[2];
#pragma unroll
            for (int h = 0; h < 2; h++) {
                s0[h] = {__shfl_sync(~0u, f[h].x, 0, 4), __shfl_sync(~0u, f[h].y, 0, 4)};
                s1[h] = {__shfl_sync(~0u, f[h].x, 1, 4), __shfl_sync(~0u, f[h].y, 1, 4)};
                s2[h] = {__shfl_sync(~0u, f[h].x, 2, 4), __shfl_sync(~0u, f[h].y, 2, 4)};
            }
#pragma unroll
            for (int h = 0; h < 2; h++) {
                s1[h] = cfma(L[h], s0[h], s1[h]);
                s2[h] = cfma(L[h], s1[h], s2[h]);
                f[h] = cfma(L[h], s2[h], f[h]);
                asm volatile("{.reg .pred p; .reg .b64 a; setp.eq.u32 p, %3, 3; mov.b64 a, {%1,%2}; @p st.relaxed.gpu.global.b64 [%0], a;}" ::"l"(cptr + h * 256),
                             "r"((__float_as_uint(f[h].x) & ~15u) | tag), "f"(f[h].y), "r"(q) : "memory");
            }
            STAMPX(2, 12);
            cf gam = lds_cf(lama + 8);
            cf st = csel(q & 2, csel(q & 1, s2[0], s1[0]), csel(q & 1, s0[0], {0.f, 0.f}));
            const cf st1 = csel(q & 2, csel(q & 1, s2[1], s1[1]), csel(q & 1, s0[1], {0.f, 0.f}));
            cptr = padd(cbase - 4 * 8192, (3 - mi) * 8192 + gl * 8);
            const int nprev = tc - 1 - mi;
            const uint8_t* hptr = padd(g_H + (size_t)(tc * 32 + wg * 16 + (cb & 6)) * 16384 + ((cb & 1) * 4 + w) * 1024, g * 64 + ((q ^ (g >> 1)) << 4));
            const uint32_t hm = 4 * (g & 1) + (q ^ (g >> 1)) == (cb & 1) * 4 + w ? ~1u : ~0u;
            float u[64];
            uint64_t fv[4] = {tag, tag, tag, tag};
            prescale<0>(u, d, gam);
            gather(fv, cptr, nprev);
#pragma unroll 1
            for (int h = 0;; h++) {
                const cf L2 = csq(L[0]), M = csq(L2);
                cf M4 = csq(csq(M));
                M4 = {__shfl_sync(~0u, M4.x, 4 * gl), __shfl_sync(~0u, M4.y, 4 * gl)};
                cf lq = cmul(gam, cmul(csel(q & 1, L[0], {1.f, 0.f}), csel(q & 2, L2, {1.f, 0.f})));
                st = cmul(gam, st);
                asm volatile("pmevent 1;" : "+f"(lq.x), "+f"(lq.y), "+f"(st.x), "+f"(st.y));
#pragma unroll 1
                for (unsigned n = 0; __any_sync(~0u, (((uint32_t)fv[0] ^ tag) | ((uint32_t)fv[1] ^ tag) | ((uint32_t)fv[2] ^ tag) | ((uint32_t)fv[3] ^ tag)) & 15u) && n < SPIN_LIMIT; n++) gather(fv, cptr, nprev);
                if (!h) STAMPX(53, 54);
                cf P = as_cf(fv[3]), pj[4];
#pragma unroll
                for (int a = 2; a >= 0; a--) P = cfma(M4, P, as_cf(fv[a]));
                cptr += 256;
                asm volatile("" : "+f"(P.x), "+f"(P.y)::"memory");
                gather(fv, cptr, h ? -1 : nprev);
#pragma unroll
                for (int j = 3; j >= 0; j--) pj[j] = {__shfl_sync(~0u, P.x, g + 8 * j), __shfl_sync(~0u, P.y, g + 8 * j)};
                st = cfma(lq, cfma(M, cfma(M, cfma(M, pj[3], pj[2]), pj[1]), pj[0]), st);
                if (!h) STAMPX(3, 13);
                uint32_t keep = sb >> 28;
                scan2(u, lam[0], st, hptr, hm, ep & ~hm, keep);
                warp_arrive(bars + B_HOWN + wg * 16 + h * 8 + keep);
                if (h) break;
                STAMPW(4, 14);
                lds128f(lama + 128, lam[0].x, lam[0].y, gam.x, gam.y);
                st = st1;
                L[0] = L[1];
                hptr += 8 * 16384;
                prescale<1>(u, d, gam);
            }
            STAMPW(5, 15);
        }
        if (wg == 0) bar_sync(4, 128); else bar_sync(8, 128);
        if (wg == 0) {
            asm volatile("setmaxnreg.dec.sync.aligned.u32 160;");
            float y[128];
            rg = ring_at(sb, role * 66 + 32);
            STAMP(6);
            STAMP(7);
            const uint64_t dA = ring_desc(sb, 0, 512, 2), dB = ring_desc(sb, 16384, 16, 1);
            gemm2(y, rg, dA, dB, 0);
            asm volatile("setmaxnreg.inc.sync.aligned.u32 184;");
            const int lane = fresh_lane(), g = lane >> 2, q = lane & 3;
            const int pg = 2 * (g & 3) + (g >> 2);
            float* op = (float*)padd(p.out + (size_t)(tc * 128 + 64 * (w & 1) + 8 * (w >> 1)) * 2048 + 1024 + cb * 128, pg * 8192 + q * 16);
            const uint32_t xa = sb + OFF_F + (16 * (w & 1) + 8 * (w >> 1) + pg) * 128 + (((q >> 1) ^ pg) << 4) + (q & 1) * 8;
#define HALF0(k) wg_fence(); peek(k < 63 ? rg.full + SL(k + 1) * 8 : bars + B_XD, PH(k + 1)); half_step<0, k>(y, dA, dB); wg_commit(); peek_wait(k < 63 ? rg.full + SL(k + 1) * 8 : bars + B_XD, PH(k + 1), rg.n);
            HALF0(60) HALF0(61) HALF0(62) HALF0(63)
            const uint64_t dB2 = ring_desc(sb >> 1, 16384, 16, 1);
            uint32_t xa0[8], xa1[8], dd[16];
#pragma unroll
            for (int i = 0; i < 8; i++) asm volatile("ld.shared.v2.b32 {%0,%1}, [%2];" : "=r"(dd[2 * i]), "=r"(dd[2 * i + 1]) : "r"(sb + OFF_LAM + q * 8 + 32 * i) : "memory");
            load_x4<0, 0>(xa0, xa);
            wg_fence();
            half_step<64, 64 - SKEW>(y, dA, dB2);
            wg_commit();
            wg_wait<1>();
#pragma unroll
            for (int i = 0; i < 64; i++) asm volatile("" : "+f"(y[i])::"memory");
            STAMP(16);
#define M1(n) if (4 + (n) < 4 * SKEW) mma_h<64, 65 - SKEW + (n) / 4, (n) % 4>(y, dA, dB2);
#define MM(n) if (4 + (n) / 2 * MPP < 4 * SKEW) { if (MPY) YIELD(); wg_fence(); M1((n) / 2 * MPP) M1((n) / 2 * MPP + 1) if (MPP > 2) { M1((n) / 2 * MPP + 2) } }
#define OUT4(R, U, X, n) out_piece<R, U>(y, dd, X[0], X[1], op); MM(n) out_piece<R, U + 1>(y, dd, X[2], X[3], op); MM(n + 2) \
                         out_piece<R, U + 2>(y, dd, X[4], X[5], op); MM(n + 4) out_piece<R, U + 3>(y, dd, X[6], X[7], op); MM(n + 6)
            load_x4<0, 4>(xa1, xa);
            OUT4(0, 0, xa0, 0)
            load_x4<1, 0>(xa0, xa);
            OUT4(0, 4, xa1, 8)
            wg_commit();
            load_x4<1, 4>(xa1, xa);
            OUT4(1, 0, xa0, 16)
            load_x4<2, 0>(xa0, xa);
            OUT4(1, 4, xa1, 16)
            STAMP(18);
            wg_wait<0>();
#pragma unroll
            for (int i = 64; i < 128; i++) asm volatile("" : "+f"(y[i])::"memory");
            STAMP(8);
            load_x4<2, 4>(xa1, xa);
            mbar_wait_fast(bars + B_XD + 8, 0);
            OUT4(2, 0, xa0, 16)
            load_x4<3, 0>(xa0, xa);
            OUT4(2, 4, xa1, 16)
            load_x4<3, 4>(xa1, xa);
            OUT4(3, 0, xa0, 16)
            OUT4(3, 4, xa1, 16)
            STAMP(9);
            return;
        }
        asm volatile("setmaxnreg.dec.sync.aligned.u32 152;");
        } else {
        if (nu) {
            constexpr int Y = YP2;
            cf T[8];
            ldtab_cf<2048>(T, TAB_T + t7 * 16);
            const uint32_t ep = get_epoch(bars);
            const int ka = pos_of(t7 >> 2);
            asm volatile("setp.eq.u32 p0, %0, 0;" ::"r"(__shfl_sync(~0u, t7, lane)));
            mbar_wait(bars + B_WSP, 0);
            mbar_wait(bars + B_FG, 0);
            uint32_t wd[4], wm[4], vo[32];
            const uint8_t* vp;
            int slot;
            const int kap0 = unit_of(role, 0, slot), al = 2 * kap0;
            const int kap1 = __shfl_sync(~0u, unit_of(role, 1, slot), 0);
            slot = __shfl_sync(~0u, slot, 0);
            cf be1 = twid(kap0 + 512 * q, 2048), be2 = csq(be1), be3 = cmul(be1, be2);
#pragma unroll
            for (int j = 0; j < 4; j++) {
                wd[j] = sb + OFF_WD + ((j + q) & 3) * WPITCH + (al & 15) + 2 * ka + 64 * q;
                wm[j] = sb + OFF_WM + (((role ? 3 : 4) - j - q) & 3) * WPITCH + (-al & 15) + 1024 - 2 * ka - 64 * q;
                wd[j] = __shfl_sync(~0u, wd[j], lane);
            }
#pragma unroll 1
            for (int u = 0; u < nu; u++) {
                const uint32_t buf = sb + OFF_P + u * 16384;
                float acc[64], za[32], zb[32], ya[32], yb[32], vv[64];
                const uint64_t dF = opaque(mkdesc(sb + OFF_F, 16, 1024, 1)), dB = opaque(mkdesc(buf, 4096, 512, 2));
                mbar_wait(bars + B_IN + u * 8, 0);
                if (!role) {
                    const uint32_t z = buf + w * 1024 + (fresh_lane() >> 2) * 128 + 64 + (fresh_lane() & 3) * 16;
#pragma unroll
                    for (int i = 0; i < 4; i++) sts128(z + i * 4096, 0, 0, 0, 0);
                    fence_async_sm();
                    bar_sync(3, 128);
                }
                STAMP3(22);
                wg_fence();
#pragma unroll
                for (int j = 0; j < 4; j++) mma128_ss<0, 0, 1>(acc, dF + j * 2, dB + j * 64, j);
                wg_commit();
                if (u) {
                    warp_arrive(bars + B_STG);
                    store_v<0, 16>(vo, vp, role || !(fresh_lane() & 4));
                    hint_v(g_cnt + 64, role);
                    if (!role) { const uint32_t t = wm[0]; wm[0] = wm[1]; wm[1] = wm[2]; wm[2] = wm[3]; wm[3] = t; }
                }
                STAMP3(39);
                wg_wait<0>();
                pin(acc);
                STAMP3(30);
                uint32_t af[16], ag[16];
#pragma unroll
                for (int k = 0; k < 8; k++) {
                    uint32_t(&o)[16] = k < 4 ? af : ag;
                    const int c = k & 3;
#pragma unroll
                    for (int b = 0; b < 2; b++) {
                        const int i = 4 * (4 * ((k >> 2) * 2 + b) + c);
                        c2 x = mul2(c2{{acc[i], acc[i + 2]}, {acc[i + 1], acc[i + 3]}}, c2{T[2 * c], T[2 * c + 1]});
                        fin<(YT >> 1)>(x);
                        o[4 * c + b] = pk(x.a.x, x.a.y);
                        o[4 * c + 2 + b] = pk(x.b.x, x.b.y);
                    }
                    asm volatile("" : "+r"(o[4 * c]), "+r"(o[4 * c + 1]), "+r"(o[4 * c + 2]), "+r"(o[4 * c + 3])::"memory");
                    wg_fence();
                    mma64_rs<0>(k < 4 ? za : zb, o[4 * c], o[4 * c + 1], o[4 * c + 2], o[4 * c + 3], dF + c * 2, c);
                    if ((YT & 1) && k < 7) YIELD();
                }
                wg_commit();
                STAMP3(31);
                mbar_wait(bars + B_WD, u & 1);
                uint32_t wr[16];
#pragma unroll
                for (int i = 0; i < 16; i++) wr[i] = lds16(wd[i >> 2] + 256 * ((i >> 1) & 1) + (i & 1) * 4 * WPITCH);
                wg_wait<0>();
                pin(za);
                pin(zb);
                pinu(af);
                pinu(ag);
                STAMP3(32);
#pragma unroll
                for (int jb = 0; jb < 4; jb++) {
                    const int i = 8 * jb;
                    c2 s0 = {{za[i], za[i + 4]}, {za[i + 1], za[i + 5]}}, s2 = {{za[i + 2], za[i + 6]}, {za[i + 3], za[i + 7]}};
                    c2 s1 = {{zb[i], zb[i + 4]}, {zb[i + 1], zb[i + 5]}}, s3 = {{zb[i + 2], zb[i + 6]}, {zb[i + 3], zb[i + 7]}};
                    s2 = mul2(s2, be1);
                    fin<Y>(s2);
                    bfly_tw<Y>(s0, s1, be2, s2, s3, be3);
                    bfly<Y>(s0, s2); bfly_mi<Y>(s1, s3);
                    c2 W[4];
#pragma unroll
                    for (int j = 0; j < 4; j++) {
                        W[j] = {{__uint_as_float(wr[4 * j] << 16), __uint_as_float(wr[4 * j + 1] << 16)}, {__uint_as_float(wr[4 * j + 2] << 16), __uint_as_float(wr[4 * j + 3] << 16)}};
                        if ((jb & 1) == 0)
                            asm volatile("@p0 ld.shared.v2.f32 {%0,%1}, [%2];" : "+f"(W[j].a.x), "+f"(W[j].a.y) : "r"(sb + OFF_WSP + u * 64 + jb * 16 + j * 8));
                    }
                    if (jb < 3) {
#pragma unroll
                        for (int k = 0; k < 16; k++) {
                            const int e = (k >> 1) & 1, pl = (k & 1) * 4 * WPITCH;
                            wr[k] = jb == 0 ? lds16(wd[k >> 2] + 512 + 256 * e + pl) : lds16(wm[k >> 2] - 512 * (jb - 1) - 256 * e + pl);
                        }
                    }
                    if (jb >= 2) {
#pragma unroll
                        for (int j = 0; j < 4; j++) { W[j].a.y = -W[j].a.y; W[j].b.y = -W[j].b.y; }
                    }
                    s0 = mul2(s0, W[0]); fin<Y>(s0);
                    s1 = mul2(s1, W[1]); fin<Y>(s1);
                    bfly_tw<Y>(s0, s2, W[2], s1, s3, W[3]);
                    bfly<Y>(s0, s1); bfly_mi<Y>(s2, s3);
                    af[4 * jb] = pk(s0.a.x, s0.b.x); af[4 * jb + 1] = pk(s3.a.x, s3.b.x); af[4 * jb + 2] = pk(s0.a.y, s0.b.y); af[4 * jb + 3] = pk(s3.a.y, s3.b.y);
                    ag[4 * jb] = pk(s1.a.x, s1.b.x); ag[4 * jb + 1] = pk(s2.a.x, s2.b.x); ag[4 * jb + 2] = pk(s1.a.y, s1.b.y); ag[4 * jb + 3] = pk(s2.a.y, s2.b.y);
                }
                pinu(af);
                pinu(ag);
                warp_arrive(bars + B_WFREE);
                wg_fence();
#pragma unroll
                for (int j = 0; j < 4; j++) mma64_rs<1>(ya, af[4 * j], af[4 * j + 1], af[4 * j + 2], af[4 * j + 3], dF + j * 128, j);
                wg_commit();
#pragma unroll
                for (int j = 0; j < 4; j++) mma64_rs<1>(yb, ag[4 * j], ag[4 * j + 1], ag[4 * j + 2], ag[4 * j + 3], dF + j * 128, j);
                wg_commit();
                STAMP3(33);
                {
                    const uint32_t a0 = buf + (mi & 1) * 4096 + (16 * w + 8 * (mi >> 1) + gl) * 64 + ((gl >> 1) << 4);
#pragma unroll
                    for (int h = 0; h < 2; h++) {
                        if (h == 0) { wg_wait<1>(); pin(ya); pinu(af); STAMP3(34); } else { wg_wait<0>(); pin(yb); pinu(ag); }
                        const float(&yy)[32] = h ? yb : ya;
#pragma unroll
                        for (int c = 0; c < 4; c++) {
                            const int i = 8 * ((c + 2 * h) & 3), k = 8 * ((c + 2 * h + 1) & 3) + 2;
                            c2 x = {cmulc({yy[i], yy[i + 1]}, T[2 * c]), cmulc({yy[k], yy[k + 1]}, T[2 * c])};
                            fin<YI & 1>(x);
                            c2 y = {cmulc({yy[i + 4], yy[i + 5]}, T[2 * c + 1]), cmulc({yy[k + 4], yy[k + 5]}, T[2 * c + 1])};
                            fin<(YI >> 1)>(y);
                            stsm4((a0 ^ (c << 4)) + h * 8192, pk(x.a.x, y.a.x), pk(x.b.x, y.b.x), pk(x.a.y, y.a.y), pk(x.b.y, y.b.y));
                        }
                    }
                }
                STAMP3(38);
                fence_async_sm();
                bar_sync(3, 128);
                wg_fence();
#pragma unroll
                for (int j = 0; j < 4; j++) mma128_ss<0, 1, 1>(vv, dF + j * 128, dB + j * 64, j);
                wg_commit();
                STAMP3(35);
                const int lane = fresh_lane(), g = lane >> 2, q = lane & 3;
                vp = padd(g_X + (4 << 20) + w * (8 * 32768) + (role ? u : 1) * 16384 + slot * 64,
                                         (g >> 1) * 32768 + (role ? g & 1 : u) * 32 + (((q ^ (slot >> 1)) & 1) << 4) + (q >> 1) * 8);
                const uint32_t tmask = (((g & 1) == ((slot >> 3) & 1) || !role) && q == ((slot >> 1) & 2)) ? ~1u : ~0u, tbit = ep & ~tmask;
                be1 = twid(kap1 + 512 * q, 2048); be2 = csq(be1); be3 = cmul(be1, be2);
                asm volatile("pmevent 1;" : "+f"(be1.x), "+f"(be1.y), "+f"(be2.x), "+f"(be2.y), "+f"(be3.x), "+f"(be3.y), "+l"(vp)::"memory");
                wg_wait<0>();
                pin(vv);
                STAMP3(36);
#pragma unroll
                for (int k = 0; k < 16; k++) {
                    const int i = 8 * (k >> 1) + 2 * (k & 1);
                    vo[2 * k] = (pk(vv[i], vv[i + 1]) & tmask) | tbit;
                    vo[2 * k + 1] = pk(vv[i + 4], vv[i + 5]);
                }
                pinu(vo);
            }
            warp_arrive(bars + B_STG);
            const bool odd = fresh_lane() & 4;
            if (!VPOS) hint_v(g_cnt + 32 + nu * 32, 1);
            store_v<0, 4>(vo, vp, role || !odd);
            if (VPOS) hint_v(g_cnt + 32 + nu * 32, 1);
            store_v<4, 16>(vo, vp, role || odd);
        }
        if (spare) return;
        }
        {
            constexpr int Y = YP3;
            uint32_t sp[8];
            cf tw[8];
            ldtab<2, 2048>(sp, TAB_SP + fb * 4096 + t7 * 16);
            ldtab_cf<16>(tw, TAB_TW3 + fb * 2048 + (t7 >> 2) * 64);
            const uint64_t dF = opaque(mkdesc(sb + OFF_F, 16, 1024, 1)), dB = opaque(mkdesc(sb + OFF_P + hf * 8192, 1024, 256, 3));
            const uint8_t* op = padd(p.out + (1024 + fb) * 2048 + fcb * 32 + hf * 16, (t7 >> 2) * 32768 + (q >> 1) * 16 + (q & 1) * 32);
            float acc[64], out[64];
            mbar_wait(bars + B_IN + 24, 0);
            mbar_wait(bars + B_FG, 1);
            STAMP(25);
            pinu(sp);
            wg_fence();
#pragma unroll
            for (int j = 0; j < 4; j++) {
                const uint64_t db = dB + (j >> 1) * 1024 + (j & 1) * 32;
                mma112_ss(acc, dF + j * 2, db + 64, j);
                if (j & 1) mma16_rs(acc, 0u, sp[2 * j], 0u, sp[2 * j + 1], db, 1);
                else mma16_rs(acc, sp[2 * j], 0u, sp[2 * j + 1], 0u, db, j);
            }
            wg_commit();
            wg_wait<0>();
            pin(acc);
            pinu(sp);
            warp_arrive(bars + B_P3M);
            if (STAG && !hf) bar_sync(5, 256);
#pragma unroll
            for (int cl = 0; cl < 2; cl++) {
                c2 z[8];
#pragma unroll
                for (int n = 0; n < 8; n++) {
                    const int i = 4 * (2 * n + cl);
                    z[n] = {{acc[i], acc[i + 2]}, {acc[i + 1], acc[i + 3]}};
                }
                z[0] = {{z[0].a.x + z[0].a.y, z[0].a.x - z[0].a.y}, {z[0].b.x + z[0].b.y, z[0].b.x - z[0].b.y}};
                z[4] = mul2(z[4], tw[4]);
                fin<Y>(z[0], z[4]);
#pragma unroll
                for (int n = 1; n < 4; n++) {
                    const cf iw = n == 1 ? cf{0.38268343236508977f, 0.92387953251128674f}
                                         : (n == 2 ? cf{0.70710678118654752f, 0.70710678118654752f} : cf{0.92387953251128674f, 0.38268343236508977f});
                    c2 y = mul2(z[n], tw[n]);
                    fin<Y>(y);
                    const cf t = {tw[8 - n].x, -tw[8 - n].y};
                    c2 E = fma2(c2{{z[8 - n].a.x, -z[8 - n].a.y}, {z[8 - n].b.x, -z[8 - n].b.y}}, t, y);
                    fin<Y>(E);
                    z[n] = fma2(twm2(y, E), iw, E);
                    fin<Y>(z[n]);
                    z[8 - n] = {{fmaf(2.f, E.a.x, -z[n].a.x), fmaf(-2.f, E.a.y, z[n].a.y)}, {fmaf(2.f, E.b.x, -z[n].b.x), fmaf(-2.f, E.b.y, z[n].b.y)}};
                }
                dft8<false, Y>(z, tw);
#pragma unroll
                for (int m = 0; m < 8; m++) {
                    out[8 * m + 2 * cl] = z[m].a.x; out[8 * m + 2 * cl + 1] = z[m].b.x;
                    out[8 * m + 4 + 2 * cl] = z[m].a.y; out[8 * m + 5 + 2 * cl] = z[m].b.y;
                }
            }
            pin(out);
            if (STAG) { if (hf) bar_arrive(5, 256); else if (STAG > 1) bar_sync(6, 256); }
            if (hf) STAMP(26);
#pragma unroll
            for (int m = 0; m < 16; m++) {
                asm volatile("st.global.v4.f32 [%0], {%1,%2,%3,%4};" ::"l"(op + (m - 8) * (1 << 20)), "f"(out[4 * m]), "f"(out[4 * m + 1]), "f"(out[4 * m + 2]), "f"(out[4 * m + 3]) : "memory");
                if (PACE_O && m < 15 && m % PACE_ON == PACE_ON - 1)
                    asm volatile("{.reg .pred p; mbarrier.test_wait.parity.shared::cta.b64 p, [%0], 0; @!p nanosleep.u32 %1;}" ::"r"(bars + B_DONE), "n"(PACE_O) : "memory");
            }
            if (STAG > 1 && hf) bar_arrive(6, 256);
            STAMP(27);
        }
    }
}

typedef CUresult (*EncodeFn)(CUtensorMap*, CUtensorMapDataType, cuuint32_t, void*, const cuuint64_t*, const cuuint64_t*, const cuuint32_t*,
                             const cuuint32_t*, CUtensorMapInterleave, CUtensorMapSwizzle, CUtensorMapL2promotion, CUtensorMapFloatOOBfill);

static CUtensorMap make_map(EncodeFn enc, const void* ptr, int rank, const cuuint64_t* dims, const cuuint64_t* strides, const cuuint32_t* box,
                            CUtensorMapSwizzle swz, CUtensorMapL2promotion promo, CUtensorMapDataType dt = CU_TENSOR_MAP_DATA_TYPE_BFLOAT16) {
    CUtensorMap m;
    const cuuint32_t es[5] = {1, 1, 1, 1, 1};
    enc(&m, dt, rank, const_cast<void*>(ptr), dims, strides, box, es, CU_TENSOR_MAP_INTERLEAVE_NONE, swz, promo,
        CU_TENSOR_MAP_FLOAT_OOB_FILL_NONE);
    return m;
}

extern "C" void kernel_launch(void* const* d_in, const int* in_sizes, int n_in, void* d_out, int out_size) {
    void* fn = nullptr;
    cudaDriverEntryPointQueryResult qr;
    cudaGetDriverEntryPoint("cuTensorMapEncodeTiled", &fn, cudaEnableDefault, &qr);
    EncodeFn enc = (EncodeFn)fn;
    void* pX;
    cudaGetSymbolAddress(&pX, g_X);
    const CUtensorMapL2promotion P256 = CU_TENSOR_MAP_L2_PROMOTION_L2_256B, P0 = CU_TENSOR_MAP_L2_PROMOTION_NONE;

    const cuuint64_t dX[5] = {1024, 2, 4, 16, 16}, sX[4] = {2048, 32 * 2048, 2 * 2048, 128 * 2048};
    const cuuint32_t bX[5] = {64, 2, 4, 16, 1};
    CUtensorMap tmX = make_map(enc, d_in[3], 5, dX, sX, bX, CU_TENSOR_MAP_SWIZZLE_128B, P256);
    const cuuint64_t dXd[4] = {64, 2048, 2, 16}, sXd[3] = {2048, 64 * 2048, 128};
    const cuuint32_t bXd[4] = {64, 16, 2, 2};
    CUtensorMap tmXd = make_map(enc, d_in[3], 4, dXd, sXd, bXd, CU_TENSOR_MAP_SWIZZLE_128B, P256);
    const cuuint64_t dB[4] = {1024, 8, 4, 32}, sB[3] = {2048, 256 * 2048, 8 * 2048};
    const cuuint32_t bB4[4] = {64, 8, 2, 4};
    CUtensorMap tmBre = make_map(enc, d_in[6], 4, dB, sB, bB4, CU_TENSOR_MAP_SWIZZLE_128B, P256);
    CUtensorMap tmBim = make_map(enc, d_in[7], 4, dB, sB, bB4, CU_TENSOR_MAP_SWIZZLE_128B, P256);
    const cuuint64_t dC[5] = {1024, 2, 4, 2, 64}, sC[4] = {2048, 4 * 2048, 2 * 2048, 16 * 2048};
    const cuuint32_t bC[5] = {64, 2, 4, 2, 4};
    CUtensorMap tmCre = make_map(enc, d_in[8], 5, dC, sC, bC, CU_TENSOR_MAP_SWIZZLE_128B, P256);
    CUtensorMap tmCim = make_map(enc, d_in[9], 5, dC, sC, bC, CU_TENSOR_MAP_SWIZZLE_128B, P256);

    const cuuint64_t dU[2] = {8192, 256}, sU[1] = {16384};
    const cuuint32_t bU[2] = {64, 64};
    CUtensorMap tmUst = make_map(enc, pX, 2, dU, sU, bU, CU_TENSOR_MAP_SWIZZLE_128B, P0);
    const cuuint64_t dF[2] = {512 * 1026 / 8, 4}, sF[1] = {512 * 1026};
    const cuuint32_t bF[2] = {WPITCH / 8, 4};
    CUtensorMap tmWr = make_map(enc, d_in[1], 2, dF, sF, bF, CU_TENSOR_MAP_SWIZZLE_NONE, P0, CU_TENSOR_MAP_DATA_TYPE_UINT64);
    CUtensorMap tmWi = make_map(enc, d_in[2], 2, dF, sF, bF, CU_TENSOR_MAP_SWIZZLE_NONE, P0, CU_TENSOR_MAP_DATA_TYPE_UINT64);

    const cuuint64_t dA[3] = {1024, 64, 32}, sA[2] = {32 * 2048, 2048};
    const cuuint32_t bA[3] = {32, 64, 1};
    CUtensorMap tmXa = make_map(enc, d_in[0], 3, dA, sA, bA, CU_TENSOR_MAP_SWIZZLE_64B, XA_PROMO);

    Params p;
    p.wr = (const __nv_bfloat16*)d_in[1];
    p.wi = (const __nv_bfloat16*)d_in[2];
    p.lre = (const __nv_bfloat16*)d_in[4];
    p.lim = (const __nv_bfloat16*)d_in[5];
    p.ldt = (const __nv_bfloat16*)d_in[10];
    p.dsk = (const __nv_bfloat16*)d_in[11];
    p.out = (float*)d_out;
    int dev = 0, sms = 0;
    cudaGetDevice(&dev);
    cudaDeviceGetAttribute(&sms, cudaDevAttrMultiProcessorCount, dev);
    auto kernel = sms == 132 ? fused_kernel<true> : fused_kernel<false>;
    cudaFuncSetAttribute(kernel, cudaFuncAttributeMaxDynamicSharedMemorySize, SMEM_BYTES);
    kernel<<<132, 512, SMEM_BYTES>>>(tmX, tmBre, tmBim, tmCre, tmCim, tmXd, tmUst, tmWr, tmWi, tmXa, p);
}
```

```cpp
#include <cuda_runtime.h>
#include <cuda.h>
#include <cuda_bf16.h>
#include <stdint.h>

#define NST 5
#define WPITCH 1056
#define OFF_P (NST * 32768)
#define OFF_F (OFF_P + 32768)
#define OFF_WD (OFF_F + 8192)
#define OFF_WM (OFF_WD + 8 * WPITCH)
#define OFF_BAR (OFF_F + 32768)
#define OFF_LAM (OFF_BAR + 432)
#define OFF_WSP (OFF_LAM + 2048)
#define OFF_PROF (OFF_WSP + 128)
#define SMEM_BYTES OFF_PROF
#define B_FULL 0
#define B_HL 40
#define B_EP 120
#define B_HR 128
#define B_XD 144
#define B_FG 160
#define B_WSP 168
#define B_WD 176
#define B_DONE 184
#define B_LD 192
#define B_RAW 200
#define B_LAM 208
#define B_IN 216
#define B_XIN 248
#define B_EMPTY 256
#define B_STG 320
#define B_WFREE 328
#define B_HOWN 336
#define B_STGU 368
#define B_P3M 384
#define B_EPOCH 416

#define PACE_U 20
#define PACE_V 20
#define XA_PACE 200
#define XA_PACE2 100
#define XA_TAB 0
#define XA_TABP 200
#define PACE_O 200
#define PACE_ON 2
#define XA_PROMO CU_TENSOR_MAP_L2_PROMOTION_L2_128B
#define TAB_T0 500
#define LAM_T0 1000
#define DEFER 1
#define UHINT 1
#define VPOS 2
#define VPOS0 8
#define GOV_T 100
#define GOV_K0 16
#define GOV_N 22
#define TIDMAP threadIdx.x
#define U1POS 2
#define WPFB B_XIN
#define VS0 16
#define YT 0
#define MPP 2
#define MPY 0
#define STAG 1
#define P1H 1
#define YI 3
#define XW 3
#define V0T 1
#define XA_N0 2
#define XA_T0 0
#define PACE_X 200
#define SKEW 4
#define SPIN_LIMIT (1u << 15)

__device__ __align__(1024) uint8_t g_X[8 << 20];
__device__ __align__(1024) uint8_t g_H[8 << 20];
__device__ __align__(1024) uint4 g_carry[16 * 512];
__device__ __align__(128) unsigned g_cnt[128];
__device__ __align__(128) unsigned g_epoch[132 * 8];

#define STAMP(i) do { } while (0)
#define STAMPO(i, o) do { } while (0)
#define STAMPW(a, b) do { } while (0)
#define STAMPX(a, b) do { } while (0)
#define STAMP5(i) do { } while (0)
#define STAMP6(i) do { } while (0)
#define STAMP3(i) do { } while (0)

#define TAB_FG 0
#define TAB_G 8192
#define TAB_F1 40960
#define TAB_T 49152
#define TAB_SP 57344
#define TAB_TW1 73728
#define TAB_TW3 75776
#define TAB_PC 83968
__device__ __align__(1024) const uint32_t g_tab[21248] = {
0x80003d80,0x80003d80,0x80003d80,0x80003d80,0x80003d80,0x80003d80,0x80003d80,0x80003d80,0x80003d80,0x80003d80,0x80003d80,0x80003d80,0x80003d80,0x80003d80,0x80003d80,0x80003d80,
0x80003d80,0x80003d80,0x80003d80,0x80003d80,0x80003d80,0x80003d80,0x80003d80,0x80003d80,0x80003d80,0x80003d80,0x80003d80,0x80003d80,0x80003d80,0x80003d80,0x80003d80,0x80003d80,
0x3d353d35,0x3d35bd35,0xbd35bd35,0xbd353d35,0x80003d80,0x3d800000,0x8000bd80,0xbd800000,0x3d353d35,0x3d35bd35,0xbd35bd35,0xbd353d35,0x80003d80,0x3d800000,0x8000bd80,0xbd800000,
0x3d353d35,0x3d35bd35,0xbd35bd35,0xbd353d35,0x80003d80,0x3d800000,0x8000bd80,0xbd800000,0x3d353d35,0x3d35bd35,0xbd35bd35,0xbd353d35,0x80003d80,0x3d800000,0x8000bd80,0xbd800000,
0x3d800000,0x3d6dbcc4,0x3d35bd35,0x3cc4bd6d,0x3d7bbc48,0x3d55bd0e,0x3d0ebd55,0x3c48bd7b,0x80003d80,0x3cc43d6d,0x3d353d35,0x3d6d3cc4,0x3c483d7b,0x3d0e3d55,0x3d553d0e,0x3d7b3c48,
0xbd800000,0xbd6d3cc4,0xbd353d35,0xbcc43d6d,0xbd7b3c48,0xbd553d0e,0xbd0e3d55,0xbc483d7b,0x8000bd80,0xbcc4bd6d,0xbd35bd35,0xbd6dbcc4,0xbc48bd7b,0xbd0ebd55,0xbd55bd0e,0xbd7bbc48,
0x3d0ebd55,0xbd7bbc48,0x3c483d7b,0x3d55bd0e,0x3d800000,0xbcc4bd6d,0xbd353d35,0x3d6d3cc4,0x3d553d0e,0x3c48bd7b,0xbd7b3c48,0x3d0e3d55,0x80003d80,0x3d6dbcc4,0xbd35bd35,0xbcc43d6d,
0xbd0e3d55,0x3d7b3c48,0xbc48bd7b,0xbd553d0e,0xbd800000,0x3cc43d6d,0x3d35bd35,0xbd6dbcc4,0xbd55bd0e,0xbc483d7b,0x3d7bbc48,0xbd0ebd55,0x8000bd80,0xbd6d3cc4,0x3d353d35,0x3cc4bd6d,
0x80003d80,0x3d353d35,0x3d800000,0x3d35bd35,0x3cc43d6d,0x3d6d3cc4,0x3d6dbcc4,0x3cc4bd6d,0x8000bd80,0xbd35bd35,0xbd800000,0xbd353d35,0xbcc4bd6d,0xbd6dbcc4,0xbd6d3cc4,0xbcc43d6d,
0x80003d80,0x3d353d35,0x3d800000,0x3d35bd35,0x3cc43d6d,0x3d6d3cc4,0x3d6dbcc4,0x3cc4bd6d,0x8000bd80,0xbd35bd35,0xbd800000,0xbd353d35,0xbcc4bd6d,0xbd6dbcc4,0xbd6d3cc4,0xbcc43d6d,
0x3d6d3cc4,0xbcc4bd6d,0xbcc43d6d,0x3d6dbcc4,0x80003d80,0x3d35bd35,0xbd800000,0x3d353d35,0xbd6dbcc4,0x3cc43d6d,0x3cc4bd6d,0xbd6d3cc4,0x8000bd80,0xbd353d35,0x3d800000,0xbd35bd35,
0x3d6d3cc4,0xbcc4bd6d,0xbcc43d6d,0x3d6dbcc4,0x80003d80,0x3d35bd35,0xbd800000,0x3d353d35,0xbd6dbcc4,0x3cc43d6d,0x3cc4bd6d,0xbd6d3cc4,0x8000bd80,0xbd353d35,0x3d800000,0xbd35bd35,
0x3d800000,0x3cc4bd6d,0xbd35bd35,0xbd6d3cc4,0x3d55bd0e,0xbc48bd7b,0xbd7bbc48,0xbd0e3d55,0x8000bd80,0xbd6dbcc4,0xbd353d35,0x3cc43d6d,0xbd0ebd55,0xbd7b3c48,0xbc483d7b,0x3d553d0e,
0xbd800000,0xbcc43d6d,0x3d353d35,0x3d6dbcc4,0xbd553d0e,0x3c483d7b,0x3d7b3c48,0x3d0ebd55,0x80003d80,0x3d6d3cc4,0x3d35bd35,0xbcc4bd6d,0x3d0e3d55,0x3d7bbc48,0x3c48bd7b,0xbd55bd0e,
0x3c48bd7b,0xbd0e3d55,0x3d55bd0e,0xbd7b3c48,0x3d800000,0xbd6dbcc4,0x3d353d35,0xbcc4bd6d,0xbd7bbc48,0x3d553d0e,0xbd0ebd55,0x3c483d7b,0x8000bd80,0xbcc43d6d,0x3d35bd35,0xbd6d3cc4,
0xbc483d7b,0x3d0ebd55,0xbd553d0e,0x3d7bbc48,0xbd800000,0x3d6d3cc4,0xbd35bd35,0x3cc43d6d,0x3d7b3c48,0xbd55bd0e,0x3d0e3d55,0xbc48bd7b,0x80003d80,0x3cc4bd6d,0xbd353d35,0x3d6dbcc4,
0x3d800000,0x3d800000,0x3d800000,0x3d800000,0x3d800000,0x3d800000,0x3d800000,0x3d800000,0x3d800000,0x3d800000,0x3d800000,0x3d800000,0x3d800000,0x3d800000,0x3d800000,0x3d800000,
0x3d800000,0x3d800000,0x3d800000,0x3d800000,0x3d800000,0x3d800000,0x3d800000,0x3d800000,0x3d800000,0x3d800000,0x3d800000,0x3d800000,0x3d800000,0x3d800000,0x3d800000,0x3d800000,
0x3d35bd35,0xbd35bd35,0xbd353d35,0x3d353d35,0x3d800000,0xbd80,0xbd800000,0x3d80,0x3d35bd35,0xbd35bd35,0xbd353d35,0x3d353d35,0x3d800000,0xbd80,0xbd800000,0x3d80,
0x3d35bd35,0xbd35bd35,0xbd353d35,0x3d353d35,0x3d800000,0xbd80,0xbd800000,0x3d80,0x3d35bd35,0xbd35bd35,0xbd353d35,0x3d353d35,0x3d800000,0xbd80,0xbd800000,0x3d80,
0xbd80,0xbcc4bd6d,0xbd35bd35,0xbd6dbcc4,0xbc48bd7b,0xbd0ebd55,0xbd55bd0e,0xbd7bbc48,0x3d800000,0x3d6dbcc4,0x3d35bd35,0x3cc4bd6d,0x3d7bbc48,0x3d55bd0e,0x3d0ebd55,0x3c48bd7b,
0x3d80,0x3cc43d6d,0x3d353d35,0x3d6d3cc4,0x3c483d7b,0x3d0e3d55,0x3d553d0e,0x3d7b3c48,0xbd800000,0xbd6d3cc4,0xbd353d35,0xbcc43d6d,0xbd7b3c48,0xbd553d0e,0xbd0e3d55,0xbc483d7b,
0xbd55bd0e,0xbc483d7b,0x3d7bbc48,0xbd0ebd55,0xbd80,0xbd6d3cc4,0x3d353d35,0x3cc4bd6d,0x3d0ebd55,0xbd7bbc48,0x3c483d7b,0x3d55bd0e,0x3d800000,0xbcc4bd6d,0xbd353d35,0x3d6d3cc4,
0x3d553d0e,0x3c48bd7b,0xbd7b3c48,0x3d0e3d55,0x3d80,0x3d6dbcc4,0xbd35bd35,0xbcc43d6d,0xbd0e3d55,0x3d7b3c48,0xbc48bd7b,0xbd553d0e,0xbd800000,0x3cc43d6d,0x3d35bd35,0xbd6dbcc4,
0x3d800000,0x3d35bd35,0xbd80,0xbd35bd35,0x3d6dbcc4,0x3cc4bd6d,0xbcc4bd6d,0xbd6dbcc4,0xbd800000,0xbd353d35,0x3d80,0x3d353d35,0xbd6d3cc4,0xbcc43d6d,0x3cc43d6d,0x3d6d3cc4,
0x3d800000,0x3d35bd35,0xbd80,0xbd35bd35,0x3d6dbcc4,0x3cc4bd6d,0xbcc4bd6d,0xbd6dbcc4,0xbd800000,0xbd353d35,0x3d80,0x3d353d35,0xbd6d3cc4,0xbcc43d6d,0x3cc43d6d,0x3d6d3cc4,
0x3cc4bd6d,0xbd6d3cc4,0x3d6d3cc4,0xbcc4bd6d,0x3d800000,0xbd35bd35,0x3d80,0x3d35bd35,0xbcc43d6d,0x3d6dbcc4,0xbd6dbcc4,0x3cc43d6d,0xbd800000,0x3d353d35,0xbd80,0xbd353d35,
0x3cc4bd6d,0xbd6d3cc4,0x3d6d3cc4,0xbcc4bd6d,0x3d800000,0xbd35bd35,0x3d80,0x3d35bd35,0xbcc43d6d,0x3d6dbcc4,0xbd6dbcc4,0x3cc43d6d,0xbd800000,0x3d353d35,0xbd80,0xbd353d35,
0xbd80,0xbd6dbcc4,0xbd353d35,0x3cc43d6d,0xbd0ebd55,0xbd7b3c48,0xbc483d7b,0x3d553d0e,0xbd800000,0xbcc43d6d,0x3d353d35,0x3d6dbcc4,0xbd553d0e,0x3c483d7b,0x3d7b3c48,0x3d0ebd55,
0x3d80,0x3d6d3cc4,0x3d35bd35,0xbcc4bd6d,0x3d0e3d55,0x3d7bbc48,0x3c48bd7b,0xbd55bd0e,0x3d800000,0x3cc4bd6d,0xbd35bd35,0xbd6d3cc4,0x3d55bd0e,0xbc48bd7b,0xbd7bbc48,0xbd0e3d55,
0xbd7bbc48,0x3d553d0e,0xbd0ebd55,0x3c483d7b,0xbd80,0xbcc43d6d,0x3d35bd35,0xbd6d3cc4,0xbc483d7b,0x3d0ebd55,0xbd553d0e,0x3d7bbc48,0xbd800000,0x3d6d3cc4,0xbd35bd35,0x3cc43d6d,
0x3d7b3c48,0xbd55bd0e,0x3d0e3d55,0xbc48bd7b,0x3d80,0x3cc4bd6d,0xbd353d35,0x3d6dbcc4,0x3c48bd7b,0xbd0e3d55,0x3d55bd0e,0xbd7b3c48,0x3d800000,0xbd6dbcc4,0x3d353d35,0xbcc4bd6d,
0x80003d80,0x8000bd80,0x80003d80,0x8000bd80,0x3d800000,0xbd800000,0x3d800000,0xbd800000,0x80003d80,0x8000bd80,0x80003d80,0x8000bd80,0x3d800000,0xbd800000,0x3d800000,0xbd800000,
0x80003d80,0x8000bd80,0x80003d80,0x8000bd80,0x3d800000,0xbd800000,0x3d800000,0xbd800000,0x80003d80,0x8000bd80,0x80003d80,0x8000bd80,0x3d800000,0xbd800000,0x3d800000,0xbd800000,
0x3d35bd35,0x3d353d35,0xbd353d35,0xbd35bd35,0x80003d80,0xbd800000,0x8000bd80,0x3d800000,0x3d35bd35,0x3d353d35,0xbd353d35,0xbd35bd35,0x80003d80,0xbd800000,0x8000bd80,0x3d800000,
0x3d35bd35,0x3d353d35,0xbd353d35,0xbd35bd35,0x80003d80,0xbd800000,0x8000bd80,0x3d800000,0x3d35bd35,0x3d353d35,0xbd353d35,0xbd35bd35,0x80003d80,0xbd800000,0x8000bd80,0x3d800000,
0x3d800000,0xbd6d3cc4,0x3d35bd35,0xbcc43d6d,0xbc48bd7b,0x3d0e3d55,0xbd55bd0e,0x3d7b3c48,0x80003d80,0xbcc4bd6d,0x3d353d35,0xbd6dbcc4,0x3d7bbc48,0xbd553d0e,0x3d0ebd55,0xbc483d7b,
0xbd800000,0x3d6dbcc4,0xbd353d35,0x3cc4bd6d,0x3c483d7b,0xbd0ebd55,0x3d553d0e,0xbd7bbc48,0x8000bd80,0x3cc43d6d,0xbd35bd35,0x3d6d3cc4,0xbd7b3c48,0x3d55bd0e,0xbd0e3d55,0x3c48bd7b,
0xbd55bd0e,0x3c48bd7b,0x3d7bbc48,0x3d0e3d55,0x3d800000,0x3cc43d6d,0xbd353d35,0xbd6dbcc4,0x3d0ebd55,0x3d7b3c48,0x3c483d7b,0xbd553d0e,0x80003d80,0xbd6d3cc4,0xbd35bd35,0x3cc4bd6d,
0x3d553d0e,0xbc483d7b,0xbd7b3c48,0xbd0ebd55,0xbd800000,0xbcc4bd6d,0x3d35bd35,0x3d6d3cc4,0xbd0e3d55,0xbd7bbc48,0xbc48bd7b,0x3d55bd0e,0x8000bd80,0x3d6dbcc4,0x3d353d35,0xbcc43d6d,
0x80003d80,0xbd35bd35,0x3d800000,0xbd353d35,0x3d6dbcc4,0xbcc43d6d,0xbcc4bd6d,0x3d6d3cc4,0x8000bd80,0x3d353d35,0xbd800000,0x3d35bd35,0xbd6d3cc4,0x3cc4bd6d,0x3cc43d6d,0xbd6dbcc4,
0x80003d80,0xbd35bd35,0x3d800000,0xbd353d35,0x3d6dbcc4,0xbcc43d6d,0xbcc4bd6d,0x3d6d3cc4,0x8000bd80,0x3d353d35,0xbd800000,0x3d35bd35,0xbd6d3cc4,0x3cc4bd6d,0x3cc43d6d,0xbd6dbcc4,
0x3cc4bd6d,0x3d6dbcc4,0x3d6d3cc4,0x3cc43d6d,0x80003d80,0xbd353d35,0xbd800000,0xbd35bd35,0xbcc43d6d,0xbd6d3cc4,0xbd6dbcc4,0xbcc4bd6d,0x8000bd80,0x3d35bd35,0x3d800000,0x3d353d35,
0x3cc4bd6d,0x3d6dbcc4,0x3d6d3cc4,0x3cc43d6d,0x80003d80,0xbd353d35,0xbd800000,0xbd35bd35,0xbcc43d6d,0xbd6d3cc4,0xbd6dbcc4,0xbcc4bd6d,0x8000bd80,0x3d35bd35,0x3d800000,0x3d353d35,
0x3d800000,0xbcc43d6d,0xbd35bd35,0x3d6dbcc4,0xbd0ebd55,0x3d7bbc48,0xbc483d7b,0xbd55bd0e,0x8000bd80,0x3d6d3cc4,0xbd353d35,0xbcc4bd6d,0xbd553d0e,0xbc48bd7b,0x3d7b3c48,0xbd0e3d55,
0xbd800000,0x3cc4bd6d,0x3d353d35,0xbd6d3cc4,0x3d0e3d55,0xbd7b3c48,0x3c48bd7b,0x3d553d0e,0x80003d80,0xbd6dbcc4,0x3d35bd35,0x3cc43d6d,0x3d55bd0e,0x3c483d7b,0xbd7bbc48,0x3d0ebd55,
0xbd7bbc48,0xbd55bd0e,0xbd0ebd55,0xbc48bd7b,0x3d800000,0x3d6d3cc4,0x3d353d35,0x3cc43d6d,0xbc483d7b,0xbd0e3d55,0xbd553d0e,0xbd7b3c48,0x8000bd80,0x3cc4bd6d,0x3d35bd35,0x3d6dbcc4,
0x3d7b3c48,0x3d553d0e,0x3d0e3d55,0x3c483d7b,0xbd800000,0xbd6dbcc4,0xbd35bd35,0xbcc4bd6d,0x3c48bd7b,0x3d0ebd55,0x3d55bd0e,0x3d7bbc48,0x80003d80,0xbcc43d6d,0xbd353d35,0xbd6d3cc4,
0x3d800000,0xbd800000,0x3d800000,0xbd800000,0xbd80,0x3d80,0xbd80,0x3d80,0x3d800000,0xbd800000,0x3d800000,0xbd800000,0xbd80,0x3d80,0xbd80,0x3d80,
0x3d800000,0xbd800000,0x3d800000,0xbd800000,0xbd80,0x3d80,0xbd80,0x3d80,0x3d800000,0xbd800000,0x3d800000,0xbd800000,0xbd80,0x3d80,0xbd80,0x3d80,
0xbd35bd35,0x3d35bd35,0x3d353d35,0xbd353d35,0x3d800000,0x3d80,0xbd800000,0xbd80,0xbd35bd35,0x3d35bd35,0x3d353d35,0xbd353d35,0x3d800000,0x3d80,0xbd800000,0xbd80,
0xbd35bd35,0x3d35bd35,0x3d353d35,0xbd353d35,0x3d800000,0x3d80,0xbd800000,0xbd80,0xbd35bd35,0x3d35bd35,0x3d353d35,0xbd353d35,0x3d800000,0x3d80,0xbd800000,0xbd80,
0xbd80,0x3cc43d6d,0xbd35bd35,0x3d6d3cc4,0xbd7b3c48,0x3d55bd0e,0xbd0e3d55,0x3c48bd7b,0x3d800000,0xbd6d3cc4,0x3d35bd35,0xbcc43d6d,0xbc48bd7b,0x3d0e3d55,0xbd55bd0e,0x3d7b3c48,
0x3d80,0xbcc4bd6d,0x3d353d35,0xbd6dbcc4,0x3d7bbc48,0xbd553d0e,0x3d0ebd55,0xbc483d7b,0xbd800000,0x3d6dbcc4,0xbd353d35,0x3cc4bd6d,0x3c483d7b,0xbd0ebd55,0x3d553d0e,0xbd7bbc48,
0xbd0e3d55,0xbd7bbc48,0xbc48bd7b,0x3d55bd0e,0xbd80,0x3d6dbcc4,0x3d353d35,0xbcc43d6d,0xbd55bd0e,0x3c48bd7b,0x3d7bbc48,0x3d0e3d55,0x3d800000,0x3cc43d6d,0xbd353d35,0xbd6dbcc4,
0x3d0ebd55,0x3d7b3c48,0x3c483d7b,0xbd553d0e,0x3d80,0xbd6d3cc4,0xbd35bd35,0x3cc4bd6d,0x3d553d0e,0xbc483d7b,0xbd7b3c48,0xbd0ebd55,0xbd800000,0xbcc4bd6d,0x3d35bd35,0x3d6d3cc4,
0x3d800000,0xbd353d35,0xbd80,0x3d353d35,0xbcc4bd6d,0x3d6d3cc4,0xbd6d3cc4,0x3cc4bd6d,0xbd800000,0x3d35bd35,0x3d80,0xbd35bd35,0x3cc43d6d,0xbd6dbcc4,0x3d6dbcc4,0xbcc43d6d,
0x3d800000,0xbd353d35,0xbd80,0x3d353d35,0xbcc4bd6d,0x3d6d3cc4,0xbd6d3cc4,0x3cc4bd6d,0xbd800000,0x3d35bd35,0x3d80,0xbd35bd35,0x3cc43d6d,0xbd6dbcc4,0x3d6dbcc4,0xbcc43d6d,
0xbd6dbcc4,0xbcc4bd6d,0x3cc4bd6d,0x3d6dbcc4,0x3d800000,0x3d353d35,0x3d80,0xbd353d35,0x3d6d3cc4,0x3cc43d6d,0xbcc43d6d,0xbd6d3cc4,0xbd800000,0xbd35bd35,0xbd80,0x3d35bd35,
0xbd6dbcc4,0xbcc4bd6d,0x3cc4bd6d,0x3d6dbcc4,0x3d800000,0x3d353d35,0x3d80,0xbd353d35,0x3d6d3cc4,0x3cc43d6d,0xbcc43d6d,0xbd6d3cc4,0xbd800000,0xbd35bd35,0xbd80,0x3d35bd35,
0xbd80,0x3d6d3cc4,0xbd353d35,0xbcc4bd6d,0xbd553d0e,0xbc48bd7b,0x3d7b3c48,0xbd0e3d55,0xbd800000,0x3cc4bd6d,0x3d353d35,0xbd6d3cc4,0x3d0e3d55,0xbd7b3c48,0x3c48bd7b,0x3d553d0e,
0x3d80,0xbd6dbcc4,0x3d35bd35,0x3cc43d6d,0x3d55bd0e,0x3c483d7b,0xbd7bbc48,0x3d0ebd55,0x3d800000,0xbcc43d6d,0xbd35bd35,0x3d6dbcc4,0xbd0ebd55,0x3d7bbc48,0xbc483d7b,0xbd55bd0e,
0xbc483d7b,0xbd0e3d55,0xbd553d0e,0xbd7b3c48,0xbd80,0x3cc4bd6d,0x3d35bd35,0x3d6dbcc4,0x3d7b3c48,0x3d553d0e,0x3d0e3d55,0x3c483d7b,0xbd800000,0xbd6dbcc4,0xbd35bd35,0xbcc4bd6d,
0x3c48bd7b,0x3d0ebd55,0x3d55bd0e,0x3d7bbc48,0x3d80,0xbcc43d6d,0xbd353d35,0xbd6d3cc4,0xbd7bbc48,0xbd55bd0e,0xbd0ebd55,0xbc48bd7b,0x3d800000,0x3d6d3cc4,0x3d353d35,0x3cc43d6d,
0x80003d80,0x80003d80,0x80003d80,0x80003d80,0x8000bd80,0x8000bd80,0x8000bd80,0x8000bd80,0x80003d80,0x80003d80,0x80003d80,0x80003d80,0x8000bd80,0x8000bd80,0x8000bd80,0x8000bd80,
0x80003d80,0x80003d80,0x80003d80,0x80003d80,0x8000bd80,0x8000bd80,0x8000bd80,0x8000bd80,0x80003d80,0x80003d80,0x80003d80,0x80003d80,0x8000bd80,0x8000bd80,0x8000bd80,0x8000bd80,
0xbd35bd35,0xbd353d35,0x3d353d35,0x3d35bd35,0x80003d80,0x3d800000,0x8000bd80,0xbd800000,0xbd35bd35,0xbd353d35,0x3d353d35,0x3d35bd35,0x80003d80,0x3d800000,0x8000bd80,0xbd800000,
0xbd35bd35,0xbd353d35,0x3d353d35,0x3d35bd35,0x80003d80,0x3d800000,0x8000bd80,0xbd800000,0xbd35bd35,0xbd353d35,0x3d353d35,0x3d35bd35,0x80003d80,0x3d800000,0x8000bd80,0xbd800000,
0x3d800000,0x3d6dbcc4,0x3d35bd35,0x3cc4bd6d,0xbd7b3c48,0xbd553d0e,0xbd0e3d55,0xbc483d7b,0x80003d80,0x3cc43d6d,0x3d353d35,0x3d6d3cc4,0xbc48bd7b,0xbd0ebd55,0xbd55bd0e,0xbd7bbc48,
0xbd800000,0xbd6d3cc4,0xbd353d35,0xbcc43d6d,0x3d7bbc48,0x3d55bd0e,0x3d0ebd55,0x3c48bd7b,0x8000bd80,0xbcc4bd6d,0xbd35bd35,0xbd6dbcc4,0x3c483d7b,0x3d0e3d55,0x3d553d0e,0x3d7b3c48,
0xbd0e3d55,0x3d7b3c48,0xbc48bd7b,0xbd553d0e,0x3d800000,0xbcc4bd6d,0xbd353d35,0x3d6d3cc4,0xbd55bd0e,0xbc483d7b,0x3d7bbc48,0xbd0ebd55,0x80003d80,0x3d6dbcc4,0xbd35bd35,0xbcc43d6d,
0x3d0ebd55,0xbd7bbc48,0x3c483d7b,0x3d55bd0e,0xbd800000,0x3cc43d6d,0x3d35bd35,0xbd6dbcc4,0x3d553d0e,0x3c48bd7b,0xbd7b3c48,0x3d0e3d55,0x8000bd80,0xbd6d3cc4,0x3d353d35,0x3cc4bd6d,
0x80003d80,0x3d353d35,0x3d800000,0x3d35bd35,0xbcc4bd6d,0xbd6dbcc4,0xbd6d3cc4,0xbcc43d6d,0x8000bd80,0xbd35bd35,0xbd800000,0xbd353d35,0x3cc43d6d,0x3d6d3cc4,0x3d6dbcc4,0x3cc4bd6d,
0x80003d80,0x3d353d35,0x3d800000,0x3d35bd35,0xbcc4bd6d,0xbd6dbcc4,0xbd6d3cc4,0xbcc43d6d,0x8000bd80,0xbd35bd35,0xbd800000,0xbd353d35,0x3cc43d6d,0x3d6d3cc4,0x3d6dbcc4,0x3cc4bd6d,
0xbd6dbcc4,0x3cc43d6d,0x3cc4bd6d,0xbd6d3cc4,0x80003d80,0x3d35bd35,0xbd800000,0x3d353d35,0x3d6d3cc4,0xbcc4bd6d,0xbcc43d6d,0x3d6dbcc4,0x8000bd80,0xbd353d35,0x3d800000,0xbd35bd35,
0xbd6dbcc4,0x3cc43d6d,0x3cc4bd6d,0xbd6d3cc4,0x80003d80,0x3d35bd35,0xbd800000,0x3d353d35,0x3d6d3cc4,0xbcc4bd6d,0xbcc43d6d,0x3d6dbcc4,0x8000bd80,0xbd353d35,0x3d800000,0xbd35bd35,
0x3d800000,0x3cc4bd6d,0xbd35bd35,0xbd6d3cc4,0xbd553d0e,0x3c483d7b,0x3d7b3c48,0x3d0ebd55,0x8000bd80,0xbd6dbcc4,0xbd353d35,0x3cc43d6d,0x3d0e3d55,0x3d7bbc48,0x3c48bd7b,0xbd55bd0e,
0xbd800000,0xbcc43d6d,0x3d353d35,0x3d6dbcc4,0x3d55bd0e,0xbc48bd7b,0xbd7bbc48,0xbd0e3d55,0x80003d80,0x3d6d3cc4,0x3d35bd35,0xbcc4bd6d,0xbd0ebd55,0xbd7b3c48,0xbc483d7b,0x3d553d0e,
0xbc483d7b,0x3d0ebd55,0xbd553d0e,0x3d7bbc48,0x3d800000,0xbd6dbcc4,0x3d353d35,0xbcc4bd6d,0x3d7b3c48,0xbd55bd0e,0x3d0e3d55,0xbc48bd7b,0x8000bd80,0xbcc43d6d,0x3d35bd35,0xbd6d3cc4,
0x3c48bd7b,0xbd0e3d55,0x3d55bd0e,0xbd7b3c48,0xbd800000,0x3d6d3cc4,0xbd35bd35,0x3cc43d6d,0xbd7bbc48,0x3d553d0e,0xbd0ebd55,0x3c483d7b,0x80003d80,0x3cc4bd6d,0xbd353d35,0x3d6dbcc4,
0x3d800000,0x3d800000,0x3d800000,0x3d800000,0xbd800000,0xbd800000,0xbd800000,0xbd800000,0x3d800000,0x3d800000,0x3d800000,0x3d800000,0xbd800000,0xbd800000,0xbd800000,0xbd800000,
0x3d800000,0x3d800000,0x3d800000,0x3d800000,0xbd800000,0xbd800000,0xbd800000,0xbd800000,0x3d800000,0x3d800000,0x3d800000,0x3d800000,0xbd800000,0xbd800000,0xbd800000,0xbd800000,
0xbd353d35,0x3d353d35,0x3d35bd35,0xbd35bd35,0x3d800000,0xbd80,0xbd800000,0x3d80,0xbd353d35,0x3d353d35,0x3d35bd35,0xbd35bd35,0x3d800000,0xbd80,0xbd800000,0x3d80,
0xbd353d35,0x3d353d35,0x3d35bd35,0xbd35bd35,0x3d800000,0xbd80,0xbd800000,0x3d80,0xbd353d35,0x3d353d35,0x3d35bd35,0xbd35bd35,0x3d800000,0xbd80,0xbd800000,0x3d80,
0xbd80,0xbcc4bd6d,0xbd35bd35,0xbd6dbcc4,0x3c483d7b,0x3d0e3d55,0x3d553d0e,0x3d7b3c48,0x3d800000,0x3d6dbcc4,0x3d35bd35,0x3cc4bd6d,0xbd7b3c48,0xbd553d0e,0xbd0e3d55,0xbc483d7b,
0x3d80,0x3cc43d6d,0x3d353d35,0x3d6d3cc4,0xbc48bd7b,0xbd0ebd55,0xbd55bd0e,0xbd7bbc48,0xbd800000,0xbd6d3cc4,0xbd353d35,0xbcc43d6d,0x3d7bbc48,0x3d55bd0e,0x3d0ebd55,0x3c48bd7b,
0x3d553d0e,0x3c48bd7b,0xbd7b3c48,0x3d0e3d55,0xbd80,0xbd6d3cc4,0x3d353d35,0x3cc4bd6d,0xbd0e3d55,0x3d7b3c48,0xbc48bd7b,0xbd553d0e,0x3d800000,0xbcc4bd6d,0xbd353d35,0x3d6d3cc4,
0xbd55bd0e,0xbc483d7b,0x3d7bbc48,0xbd0ebd55,0x3d80,0x3d6dbcc4,0xbd35bd35,0xbcc43d6d,0x3d0ebd55,0xbd7bbc48,0x3c483d7b,0x3d55bd0e,0xbd800000,0x3cc43d6d,0x3d35bd35,0xbd6dbcc4,
0x3d800000,0x3d35bd35,0xbd80,0xbd35bd35,0xbd6d3cc4,0xbcc43d6d,0x3cc43d6d,0x3d6d3cc4,0xbd800000,0xbd353d35,0x3d80,0x3d353d35,0x3d6dbcc4,0x3cc4bd6d,0xbcc4bd6d,0xbd6dbcc4,
0x3d800000,0x3d35bd35,0xbd80,0xbd35bd35,0xbd6d3cc4,0xbcc43d6d,0x3cc43d6d,0x3d6d3cc4,0xbd800000,0xbd353d35,0x3d80,0x3d353d35,0x3d6dbcc4,0x3cc4bd6d,0xbcc4bd6d,0xbd6dbcc4,
0xbcc43d6d,0x3d6dbcc4,0xbd6dbcc4,0x3cc43d6d,0x3d800000,0xbd35bd35,0x3d80,0x3d35bd35,0x3cc4bd6d,0xbd6d3cc4,0x3d6d3cc4,0xbcc4bd6d,0xbd800000,0x3d353d35,0xbd80,0xbd353d35,
0xbcc43d6d,0x3d6dbcc4,0xbd6dbcc4,0x3cc43d6d,0x3d800000,0xbd35bd35,0x3d80,0x3d35bd35,0x3cc4bd6d,0xbd6d3cc4,0x3d6d3cc4,0xbcc4bd6d,0xbd800000,0x3d353d35,0xbd80,0xbd353d35,
0xbd80,0xbd6dbcc4,0xbd353d35,0x3cc43d6d,0x3d0e3d55,0x3d7bbc48,0x3c48bd7b,0xbd55bd0e,0xbd800000,0xbcc43d6d,0x3d353d35,0x3d6dbcc4,0x3d55bd0e,0xbc48bd7b,0xbd7bbc48,0xbd0e3d55,
0x3d80,0x3d6d3cc4,0x3d35bd35,0xbcc4bd6d,0xbd0ebd55,0xbd7b3c48,0xbc483d7b,0x3d553d0e,0x3d800000,0x3cc4bd6d,0xbd35bd35,0xbd6d3cc4,0xbd553d0e,0x3c483d7b,0x3d7b3c48,0x3d0ebd55,
0x3d7b3c48,0xbd55bd0e,0x3d0e3d55,0xbc48bd7b,0xbd80,0xbcc43d6d,0x3d35bd35,0xbd6d3cc4,0x3c48bd7b,0xbd0e3d55,0x3d55bd0e,0xbd7b3c48,0xbd800000,0x3d6d3cc4,0xbd35bd35,0x3cc43d6d,
0xbd7bbc48,0x3d553d0e,0xbd0ebd55,0x3c483d7b,0x3d80,0x3cc4bd6d,0xbd353d35,0x3d6dbcc4,0xbc483d7b,0x3d0ebd55,0xbd553d0e,0x3d7bbc48,0x3d800000,0xbd6dbcc4,0x3d353d35,0xbcc4bd6d,
0x80003d80,0x8000bd80,0x80003d80,0x8000bd80,0xbd800000,0x3d800000,0xbd800000,0x3d800000,0x80003d80,0x8000bd80,0x80003d80,0x8000bd80,0xbd800000,0x3d800000,0xbd800000,0x3d800000,
0x80003d80,0x8000bd80,0x80003d80,0x8000bd80,0xbd800000,0x3d800000,0xbd800000,0x3d800000,0x80003d80,0x8000bd80,0x80003d80,0x8000bd80,0xbd800000,0x3d800000,0xbd800000,0x3d800000,
0xbd353d35,0xbd35bd35,0x3d35bd35,0x3d353d35,0x80003d80,0xbd800000,0x8000bd80,0x3d800000,0xbd353d35,0xbd35bd35,0x3d35bd35,0x3d353d35,0x80003d80,0xbd800000,0x8000bd80,0x3d800000,
0xbd353d35,0xbd35bd35,0x3d35bd35,0x3d353d35,0x80003d80,0xbd800000,0x8000bd80,0x3d800000,0xbd353d35,0xbd35bd35,0x3d35bd35,0x3d353d35,0x80003d80,0xbd800000,0x8000bd80,0x3d800000,
0x3d800000,0xbd6d3cc4,0x3d35bd35,0xbcc43d6d,0x3c483d7b,0xbd0ebd55,0x3d553d0e,0xbd7bbc48,0x80003d80,0xbcc4bd6d,0x3d353d35,0xbd6dbcc4,0xbd7b3c48,0x3d55bd0e,0xbd0e3d55,0x3c48bd7b,
0xbd800000,0x3d6dbcc4,0xbd353d35,0x3cc4bd6d,0xbc48bd7b,0x3d0e3d55,0xbd55bd0e,0x3d7b3c48,0x8000bd80,0x3cc43d6d,0xbd35bd35,0x3d6d3cc4,0x3d7bbc48,0xbd553d0e,0x3d0ebd55,0xbc483d7b,
0x3d553d0e,0xbc483d7b,0xbd7b3c48,0xbd0ebd55,0x3d800000,0x3cc43d6d,0xbd353d35,0xbd6dbcc4,0xbd0e3d55,0xbd7bbc48,0xbc48bd7b,0x3d55bd0e,0x80003d80,0xbd6d3cc4,0xbd35bd35,0x3cc4bd6d,
0xbd55bd0e,0x3c48bd7b,0x3d7bbc48,0x3d0e3d55,0xbd800000,0xbcc4bd6d,0x3d35bd35,0x3d6d3cc4,0x3d0ebd55,0x3d7b3c48,0x3c483d7b,0xbd553d0e,0x8000bd80,0x3d6dbcc4,0x3d353d35,0xbcc43d6d,
0x80003d80,0xbd35bd35,0x3d800000,0xbd353d35,0xbd6d3cc4,0x3cc4bd6d,0x3cc43d6d,0xbd6dbcc4,0x8000bd80,0x3d353d35,0xbd800000,0x3d35bd35,0x3d6dbcc4,0xbcc43d6d,0xbcc4bd6d,0x3d6d3cc4,
0x80003d80,0xbd35bd35,0x3d800000,0xbd353d35,0xbd6d3cc4,0x3cc4bd6d,0x3cc43d6d,0xbd6dbcc4,0x8000bd80,0x3d353d35,0xbd800000,0x3d35bd35,0x3d6dbcc4,0xbcc43d6d,0xbcc4bd6d,0x3d6d3cc4,
0xbcc43d6d,0xbd6d3cc4,0xbd6dbcc4,0xbcc4bd6d,0x80003d80,0xbd353d35,0xbd800000,0xbd35bd35,0x3cc4bd6d,0x3d6dbcc4,0x3d6d3cc4,0x3cc43d6d,0x8000bd80,0x3d35bd35,0x3d800000,0x3d353d35,
0xbcc43d6d,0xbd6d3cc4,0xbd6dbcc4,0xbcc4bd6d,0x80003d80,0xbd353d35,0xbd800000,0xbd35bd35,0x3cc4bd6d,0x3d6dbcc4,0x3d6d3cc4,0x3cc43d6d,0x8000bd80,0x3d35bd35,0x3d800000,0x3d353d35,
0x3d800000,0xbcc43d6d,0xbd35bd35,0x3d6dbcc4,0x3d0e3d55,0xbd7b3c48,0x3c48bd7b,0x3d553d0e,0x8000bd80,0x3d6d3cc4,0xbd353d35,0xbcc4bd6d,0x3d55bd0e,0x3c483d7b,0xbd7bbc48,0x3d0ebd55,
0xbd800000,0x3cc4bd6d,0x3d353d35,0xbd6d3cc4,0xbd0ebd55,0x3d7bbc48,0xbc483d7b,0xbd55bd0e,0x80003d80,0xbd6dbcc4,0x3d35bd35,0x3cc43d6d,0xbd553d0e,0xbc48bd7b,0x3d7b3c48,0xbd0e3d55,
0x3d7b3c48,0x3d553d0e,0x3d0e3d55,0x3c483d7b,0x3d800000,0x3d6d3cc4,0x3d353d35,0x3cc43d6d,0x3c48bd7b,0x3d0ebd55,0x3d55bd0e,0x3d7bbc48,0x8000bd80,0x3cc4bd6d,0x3d35bd35,0x3d6dbcc4,
0xbd7bbc48,0xbd55bd0e,0xbd0ebd55,0xbc48bd7b,0xbd800000,0xbd6dbcc4,0xbd35bd35,0xbcc4bd6d,0xbc483d7b,0xbd0e3d55,0xbd553d0e,0xbd7b3c48,0x80003d80,0xbcc43d6d,0xbd353d35,0xbd6d3cc4,
0x3d800000,0xbd800000,0x3d800000,0xbd800000,0x3d80,0xbd80,0x3d80,0xbd80,0x3d800000,0xbd800000,0x3d800000,0xbd800000,0x3d80,0xbd80,0x3d80,0xbd80,
0x3d800000,0xbd800000,0x3d800000,0xbd800000,0x3d80,0xbd80,0x3d80,0xbd80,0x3d800000,0xbd800000,0x3d800000,0xbd800000,0x3d80,0xbd80,0x3d80,0xbd80,
0x3d353d35,0xbd353d35,0xbd35bd35,0x3d35bd35,0x3d800000,0x3d80,0xbd800000,0xbd80,0x3d353d35,0xbd353d35,0xbd35bd35,0x3d35bd35,0x3d800000,0x3d80,0xbd800000,0xbd80,
0x3d353d35,0xbd353d35,0xbd35bd35,0x3d35bd35,0x3d800000,0x3d80,0xbd800000,0xbd80,0x3d353d35,0xbd353d35,0xbd35bd35,0x3d35bd35,0x3d800000,0x3d80,0xbd800000,0xbd80,
0xbd80,0x3cc43d6d,0xbd35bd35,0x3d6d3cc4,0x3d7bbc48,0xbd553d0e,0x3d0ebd55,0xbc483d7b,0x3d800000,0xbd6d3cc4,0x3d35bd35,0xbcc43d6d,0x3c483d7b,0xbd0ebd55,0x3d553d0e,0xbd7bbc48,
0x3d80,0xbcc4bd6d,0x3d353d35,0xbd6dbcc4,0xbd7b3c48,0x3d55bd0e,0xbd0e3d55,0x3c48bd7b,0xbd800000,0x3d6dbcc4,0xbd353d35,0x3cc4bd6d,0xbc48bd7b,0x3d0e3d55,0xbd55bd0e,0x3d7b3c48,
0x3d0ebd55,0x3d7b3c48,0x3c483d7b,0xbd553d0e,0xbd80,0x3d6dbcc4,0x3d353d35,0xbcc43d6d,0x3d553d0e,0xbc483d7b,0xbd7b3c48,0xbd0ebd55,0x3d800000,0x3cc43d6d,0xbd353d35,0xbd6dbcc4,
0xbd0e3d55,0xbd7bbc48,0xbc48bd7b,0x3d55bd0e,0x3d80,0xbd6d3cc4,0xbd35bd35,0x3cc4bd6d,0xbd55bd0e,0x3c48bd7b,0x3d7bbc48,0x3d0e3d55,0xbd800000,0xbcc4bd6d,0x3d35bd35,0x3d6d3cc4,
0x3d800000,0xbd353d35,0xbd80,0x3d353d35,0x3cc43d6d,0xbd6dbcc4,0x3d6dbcc4,0xbcc43d6d,0xbd800000,0x3d35bd35,0x3d80,0xbd35bd35,0xbcc4bd6d,0x3d6d3cc4,0xbd6d3cc4,0x3cc4bd6d,
0x3d800000,0xbd353d35,0xbd80,0x3d353d35,0x3cc43d6d,0xbd6dbcc4,0x3d6dbcc4,0xbcc43d6d,0xbd800000,0x3d35bd35,0x3d80,0xbd35bd35,0xbcc4bd6d,0x3d6d3cc4,0xbd6d3cc4,0x3cc4bd6d,
0x3d6d3cc4,0x3cc43d6d,0xbcc43d6d,0xbd6d3cc4,0x3d800000,0x3d353d35,0x3d80,0xbd353d35,0xbd6dbcc4,0xbcc4bd6d,0x3cc4bd6d,0x3d6dbcc4,0xbd800000,0xbd35bd35,0xbd80,0x3d35bd35,
0x3d6d3cc4,0x3cc43d6d,0xbcc43d6d,0xbd6d3cc4,0x3d800000,0x3d353d35,0x3d80,0xbd353d35,0xbd6dbcc4,0xbcc4bd6d,0x3cc4bd6d,0x3d6dbcc4,0xbd800000,0xbd35bd35,0xbd80,0x3d35bd35,
0xbd80,0x3d6d3cc4,0xbd353d35,0xbcc4bd6d,0x3d55bd0e,0x3c483d7b,0xbd7bbc48,0x3d0ebd55,0xbd800000,0x3cc4bd6d,0x3d353d35,0xbd6d3cc4,0xbd0ebd55,0x3d7bbc48,0xbc483d7b,0xbd55bd0e,
0x3d80,0xbd6dbcc4,0x3d35bd35,0x3cc43d6d,0xbd553d0e,0xbc48bd7b,0x3d7b3c48,0xbd0e3d55,0x3d800000,0xbcc43d6d,0xbd35bd35,0x3d6dbcc4,0x3d0e3d55,0xbd7b3c48,0x3c48bd7b,0x3d553d0e,
0x3c48bd7b,0x3d0ebd55,0x3d55bd0e,0x3d7bbc48,0xbd80,0x3cc4bd6d,0x3d35bd35,0x3d6dbcc4,0xbd7bbc48,0xbd55bd0e,0xbd0ebd55,0xbc48bd7b,0xbd800000,0xbd6dbcc4,0xbd35bd35,0xbcc4bd6d,
0xbc483d7b,0xbd0e3d55,0xbd553d0e,0xbd7b3c48,0x3d80,0xbcc43d6d,0xbd353d35,0xbd6d3cc4,0x3d7b3c48,0x3d553d0e,0x3d0e3d55,0x3c483d7b,0x3d800000,0x3d6d3cc4,0x3d353d35,0x3cc43d6d,
0x3d80,0x3d80,0x3d80,0x3d80,0x3d80,0x3d80,0x3d80,0x3d80,0x3d80,0x3d80,0x3d80,0x3d80,0x3d80,0x3d80,0x3d80,0x3d80,
0x3d80,0x3d80,0x3d80,0x3d80,0x3d80,0x3d80,0x3d80,0x3d80,0x3d80,0x3d80,0x3d80,0x3d80,0x3d80,0x3d80,0x3d80,0x3d80,
0xbd353d35,0xbd553d0e,0xbd6d3cc4,0xbd7b3c48,0x3d80,0xbc483d7b,0xbcc43d6d,0xbd0e3d55,0xbd35bd35,0xbd0ebd55,0xbcc4bd6d,0xbc48bd7b,0xbd800000,0xbd7bbc48,0xbd6dbcc4,0xbd55bd0e,
0x3d35bd35,0x3d55bd0e,0x3d6dbcc4,0x3d7bbc48,0xbd80,0x3c48bd7b,0x3cc4bd6d,0x3d0ebd55,0x3d353d35,0x3d0e3d55,0x3cc43d6d,0x3c483d7b,0x3d800000,0x3d7b3c48,0x3d6d3cc4,0x3d553d0e,
0xbd80,0x3cc4bd6d,0x3d35bd35,0x3d6dbcc4,0x3d800000,0x3d6d3cc4,0x3d353d35,0x3cc43d6d,0x3d80,0xbcc43d6d,0xbd353d35,0xbd6d3cc4,0xbd800000,0xbd6dbcc4,0xbd35bd35,0xbcc4bd6d,
0xbd80,0x3cc4bd6d,0x3d35bd35,0x3d6dbcc4,0x3d800000,0x3d6d3cc4,0x3d353d35,0x3cc43d6d,0x3d80,0xbcc43d6d,0xbd353d35,0xbd6d3cc4,0xbd800000,0xbd6dbcc4,0xbd35bd35,0xbcc4bd6d,
0xbd353d35,0xbd7b3c48,0xbd6dbcc4,0xbd0ebd55,0x3d800000,0x3d553d0e,0x3cc43d6d,0xbc483d7b,0xbd35bd35,0xbc48bd7b,0x3cc4bd6d,0x3d55bd0e,0x3d80,0xbd0e3d55,0xbd6d3cc4,0xbd7bbc48,
0x3d35bd35,0x3d7bbc48,0x3d6d3cc4,0x3d0e3d55,0xbd800000,0xbd55bd0e,0xbcc4bd6d,0x3c48bd7b,0x3d353d35,0x3c483d7b,0xbcc43d6d,0xbd553d0e,0xbd80,0x3d0ebd55,0x3d6dbcc4,0x3d7b3c48,
0x3d80,0xbd353d35,0xbd800000,0xbd35bd35,0xbd80,0x3d35bd35,0x3d800000,0x3d353d35,0x3d80,0xbd353d35,0xbd800000,0xbd35bd35,0xbd80,0x3d35bd35,0x3d800000,0x3d353d35,
0x3d80,0xbd353d35,0xbd800000,0xbd35bd35,0xbd80,0x3d35bd35,0x3d800000,0x3d353d35,0x3d80,0xbd353d35,0xbd800000,0xbd35bd35,0xbd80,0x3d35bd35,0x3d800000,0x3d353d35,
0xbd353d35,0xbd7bbc48,0xbcc4bd6d,0x3d0ebd55,0xbd80,0x3d55bd0e,0x3d6d3cc4,0x3c483d7b,0xbd35bd35,0x3c48bd7b,0x3d6dbcc4,0x3d553d0e,0x3d800000,0x3d0e3d55,0xbcc43d6d,0xbd7b3c48,
0x3d35bd35,0x3d7b3c48,0x3cc43d6d,0xbd0e3d55,0x3d80,0xbd553d0e,0xbd6dbcc4,0xbc48bd7b,0x3d353d35,0xbc483d7b,0xbd6d3cc4,0xbd55bd0e,0xbd800000,0xbd0ebd55,0x3cc4bd6d,0x3d7bbc48,
0xbd80,0x3d6dbcc4,0x3d353d35,0xbcc43d6d,0xbd800000,0xbcc4bd6d,0x3d35bd35,0x3d6d3cc4,0x3d80,0xbd6d3cc4,0xbd35bd35,0x3cc4bd6d,0x3d800000,0x3cc43d6d,0xbd353d35,0xbd6dbcc4,
0xbd80,0x3d6dbcc4,0x3d353d35,0xbcc43d6d,0xbd800000,0xbcc4bd6d,0x3d35bd35,0x3d6d3cc4,0x3d80,0xbd6d3cc4,0xbd35bd35,0x3cc4bd6d,0x3d800000,0x3cc43d6d,0xbd353d35,0xbd6dbcc4,
0xbd353d35,0xbd55bd0e,0x3cc4bd6d,0x3d7b3c48,0xbd800000,0xbc48bd7b,0x3d6dbcc4,0x3d0e3d55,0xbd35bd35,0x3d0ebd55,0x3d6d3cc4,0xbc483d7b,0xbd80,0x3d7bbc48,0x3cc43d6d,0xbd553d0e,
0x3d35bd35,0x3d553d0e,0xbcc43d6d,0xbd7bbc48,0x3d800000,0x3c483d7b,0xbd6d3cc4,0xbd0ebd55,0x3d353d35,0xbd0e3d55,0xbd6dbcc4,0x3c48bd7b,0x3d80,0xbd7b3c48,0xbcc4bd6d,0x3d55bd0e,
0xbd800000,0xbd800000,0xbd800000,0xbd800000,0xbd800000,0xbd800000,0xbd800000,0xbd800000,0xbd800000,0xbd800000,0xbd800000,0xbd800000,0xbd800000,0xbd800000,0xbd800000,0xbd800000,
0xbd800000,0xbd800000,0xbd800000,0xbd800000,0xbd800000,0xbd800000,0xbd800000,0xbd800000,0xbd800000,0xbd800000,0xbd800000,0xbd800000,0xbd800000,0xbd800000,0xbd800000,0xbd800000,
0xbd35bd35,0xbd0ebd55,0xbcc4bd6d,0xbc48bd7b,0xbd800000,0xbd7bbc48,0xbd6dbcc4,0xbd55bd0e,0x3d35bd35,0x3d55bd0e,0x3d6dbcc4,0x3d7bbc48,0x8000bd80,0x3c48bd7b,0x3cc4bd6d,0x3d0ebd55,
0x3d353d35,0x3d0e3d55,0x3cc43d6d,0x3c483d7b,0x3d800000,0x3d7b3c48,0x3d6d3cc4,0x3d553d0e,0xbd353d35,0xbd553d0e,0xbd6d3cc4,0xbd7b3c48,0x80003d80,0xbc483d7b,0xbcc43d6d,0xbd0e3d55,
0x3d800000,0x3d6d3cc4,0x3d353d35,0x3cc43d6d,0x80003d80,0xbcc43d6d,0xbd353d35,0xbd6d3cc4,0xbd800000,0xbd6dbcc4,0xbd35bd35,0xbcc4bd6d,0x8000bd80,0x3cc4bd6d,0x3d35bd35,0x3d6dbcc4,
0x3d800000,0x3d6d3cc4,0x3d353d35,0x3cc43d6d,0x80003d80,0xbcc43d6d,0xbd353d35,0xbd6d3cc4,0xbd800000,0xbd6dbcc4,0xbd35bd35,0xbcc4bd6d,0x8000bd80,0x3cc4bd6d,0x3d35bd35,0x3d6dbcc4,
0xbd35bd35,0xbc48bd7b,0x3cc4bd6d,0x3d55bd0e,0x80003d80,0xbd0e3d55,0xbd6d3cc4,0xbd7bbc48,0x3d35bd35,0x3d7bbc48,0x3d6d3cc4,0x3d0e3d55,0xbd800000,0xbd55bd0e,0xbcc4bd6d,0x3c48bd7b,
0x3d353d35,0x3c483d7b,0xbcc43d6d,0xbd553d0e,0x8000bd80,0x3d0ebd55,0x3d6dbcc4,0x3d7b3c48,0xbd353d35,0xbd7b3c48,0xbd6dbcc4,0xbd0ebd55,0x3d800000,0x3d553d0e,0x3cc43d6d,0xbc483d7b,
0xbd800000,0xbd35bd35,0x8000bd80,0x3d35bd35,0x3d800000,0x3d353d35,0x80003d80,0xbd353d35,0xbd800000,0xbd35bd35,0x8000bd80,0x3d35bd35,0x3d800000,0x3d353d35,0x80003d80,0xbd353d35,
0xbd800000,0xbd35bd35,0x8000bd80,0x3d35bd35,0x3d800000,0x3d353d35,0x80003d80,0xbd353d35,0xbd800000,0xbd35bd35,0x8000bd80,0x3d35bd35,0x3d800000,0x3d353d35,0x80003d80,0xbd353d35,
0xbd35bd35,0x3c48bd7b,0x3d6dbcc4,0x3d553d0e,0x3d800000,0x3d0e3d55,0xbcc43d6d,0xbd7b3c48,0x3d35bd35,0x3d7b3c48,0x3cc43d6d,0xbd0e3d55,0x80003d80,0xbd553d0e,0xbd6dbcc4,0xbc48bd7b,
0x3d353d35,0xbc483d7b,0xbd6d3cc4,0xbd55bd0e,0xbd800000,0xbd0ebd55,0x3cc4bd6d,0x3d7bbc48,0xbd353d35,0xbd7bbc48,0xbcc4bd6d,0x3d0ebd55,0x8000bd80,0x3d55bd0e,0x3d6d3cc4,0x3c483d7b,
0x3d800000,0x3cc43d6d,0xbd353d35,0xbd6dbcc4,0x8000bd80,0x3d6dbcc4,0x3d353d35,0xbcc43d6d,0xbd800000,0xbcc4bd6d,0x3d35bd35,0x3d6d3cc4,0x80003d80,0xbd6d3cc4,0xbd35bd35,0x3cc4bd6d,
0x3d800000,0x3cc43d6d,0xbd353d35,0xbd6dbcc4,0x8000bd80,0x3d6dbcc4,0x3d353d35,0xbcc43d6d,0xbd800000,0xbcc4bd6d,0x3d35bd35,0x3d6d3cc4,0x80003d80,0xbd6d3cc4,0xbd35bd35,0x3cc4bd6d,
0xbd35bd35,0x3d0ebd55,0x3d6d3cc4,0xbc483d7b,0x8000bd80,0x3d7bbc48,0x3cc43d6d,0xbd553d0e,0x3d35bd35,0x3d553d0e,0xbcc43d6d,0xbd7bbc48,0x3d800000,0x3c483d7b,0xbd6d3cc4,0xbd0ebd55,
0x3d353d35,0xbd0e3d55,0xbd6dbcc4,0x3c48bd7b,0x80003d80,0xbd7b3c48,0xbcc4bd6d,0x3d55bd0e,0xbd353d35,0xbd55bd0e,0x3cc4bd6d,0x3d7b3c48,0xbd800000,0xbc48bd7b,0x3d6dbcc4,0x3d0e3d55,
0x3d80,0xbd800000,0xbd80,0x3d800000,0x3d80,0xbd800000,0xbd80,0x3d800000,0x3d80,0xbd800000,0xbd80,0x3d800000,0x3d80,0xbd800000,0xbd80,0x3d800000,
0x3d80,0xbd800000,0xbd80,0x3d800000,0x3d80,0xbd800000,0xbd80,0x3d800000,0x3d80,0xbd800000,0xbd80,0x3d800000,0x3d80,0xbd800000,0xbd80,0x3d800000,
0xbd353d35,0xbd0ebd55,0x3d6dbcc4,0x3c483d7b,0x3d80,0xbd7bbc48,0x3cc4bd6d,0x3d553d0e,0xbd35bd35,0x3d55bd0e,0x3cc43d6d,0xbd7b3c48,0xbd800000,0x3c48bd7b,0x3d6d3cc4,0xbd0e3d55,
0x3d35bd35,0x3d0e3d55,0xbd6d3cc4,0xbc48bd7b,0xbd80,0x3d7b3c48,0xbcc43d6d,0xbd55bd0e,0x3d353d35,0xbd553d0e,0xbcc4bd6d,0x3d7bbc48,0x3d800000,0xbc483d7b,0xbd6dbcc4,0x3d0ebd55,
0xbd80,0x3d6d3cc4,0xbd353d35,0xbcc4bd6d,0x3d800000,0xbcc43d6d,0xbd35bd35,0x3d6dbcc4,0x3d80,0xbd6dbcc4,0x3d35bd35,0x3cc43d6d,0xbd800000,0x3cc4bd6d,0x3d353d35,0xbd6d3cc4,
0xbd80,0x3d6d3cc4,0xbd353d35,0xbcc4bd6d,0x3d800000,0xbcc43d6d,0xbd35bd35,0x3d6dbcc4,0x3d80,0xbd6dbcc4,0x3d35bd35,0x3cc43d6d,0xbd800000,0x3cc4bd6d,0x3d353d35,0xbd6d3cc4,
0xbd353d35,0xbc48bd7b,0x3d6d3cc4,0xbd553d0e,0x3d800000,0xbd0e3d55,0xbcc4bd6d,0x3d7b3c48,0xbd35bd35,0x3d7bbc48,0xbcc43d6d,0xbd0ebd55,0x3d80,0xbd55bd0e,0x3d6dbcc4,0xbc483d7b,
0x3d35bd35,0x3c483d7b,0xbd6dbcc4,0x3d55bd0e,0xbd800000,0x3d0ebd55,0x3cc43d6d,0xbd7bbc48,0x3d353d35,0xbd7b3c48,0x3cc4bd6d,0x3d0e3d55,0xbd80,0x3d553d0e,0xbd6d3cc4,0x3c48bd7b,
0x3d80,0xbd35bd35,0x3d800000,0xbd353d35,0xbd80,0x3d353d35,0xbd800000,0x3d35bd35,0x3d80,0xbd35bd35,0x3d800000,0xbd353d35,0xbd80,0x3d353d35,0xbd800000,0x3d35bd35,
0x3d80,0xbd35bd35,0x3d800000,0xbd353d35,0xbd80,0x3d353d35,0xbd800000,0x3d35bd35,0x3d80,0xbd35bd35,0x3d800000,0xbd353d35,0xbd80,0x3d353d35,0xbd800000,0x3d35bd35,
0xbd353d35,0x3c48bd7b,0x3cc43d6d,0xbd55bd0e,0xbd80,0x3d0e3d55,0xbd6dbcc4,0x3d7bbc48,0xbd35bd35,0x3d7b3c48,0xbd6d3cc4,0x3d0ebd55,0x3d800000,0xbd553d0e,0x3cc4bd6d,0x3c483d7b,
0x3d35bd35,0xbc483d7b,0xbcc4bd6d,0x3d553d0e,0x3d80,0xbd0ebd55,0x3d6d3cc4,0xbd7b3c48,0x3d353d35,0xbd7bbc48,0x3d6dbcc4,0xbd0e3d55,0xbd800000,0x3d55bd0e,0xbcc43d6d,0xbc48bd7b,
0xbd80,0x3cc43d6d,0xbd35bd35,0x3d6d3cc4,0xbd800000,0x3d6dbcc4,0xbd353d35,0x3cc4bd6d,0x3d80,0xbcc4bd6d,0x3d353d35,0xbd6dbcc4,0x3d800000,0xbd6d3cc4,0x3d35bd35,0xbcc43d6d,
0xbd80,0x3cc43d6d,0xbd35bd35,0x3d6d3cc4,0xbd800000,0x3d6dbcc4,0xbd353d35,0x3cc4bd6d,0x3d80,0xbcc4bd6d,0x3d353d35,0xbd6dbcc4,0x3d800000,0xbd6d3cc4,0x3d35bd35,0xbcc43d6d,
0xbd353d35,0x3d0ebd55,0xbcc43d6d,0x3c48bd7b,0xbd800000,0x3d7bbc48,0xbd6d3cc4,0x3d55bd0e,0xbd35bd35,0x3d553d0e,0xbd6dbcc4,0x3d7b3c48,0xbd80,0x3c483d7b,0xbcc4bd6d,0x3d0e3d55,
0x3d35bd35,0xbd0e3d55,0x3cc4bd6d,0xbc483d7b,0x3d800000,0xbd7b3c48,0x3d6dbcc4,0xbd553d0e,0x3d353d35,0xbd55bd0e,0x3d6d3cc4,0xbd7bbc48,0x3d80,0xbc48bd7b,0x3cc43d6d,0xbd0ebd55,
0xbd800000,0x8000bd80,0x3d800000,0x80003d80,0xbd800000,0x8000bd80,0x3d800000,0x80003d80,0xbd800000,0x8000bd80,0x3d800000,0x80003d80,0xbd800000,0x8000bd80,0x3d800000,0x80003d80,
0xbd800000,0x8000bd80,0x3d800000,0x80003d80,0xbd800000,0x8000bd80,0x3d800000,0x80003d80,0xbd800000,0x8000bd80,0x3d800000,0x80003d80,0xbd800000,0x8000bd80,0x3d800000,0x80003d80,
0xbd35bd35,0x3d55bd0e,0x3cc43d6d,0xbd7b3c48,0xbd800000,0x3c48bd7b,0x3d6d3cc4,0xbd0e3d55,0x3d35bd35,0x3d0e3d55,0xbd6d3cc4,0xbc48bd7b,0x8000bd80,0x3d7b3c48,0xbcc43d6d,0xbd55bd0e,
0x3d353d35,0xbd553d0e,0xbcc4bd6d,0x3d7bbc48,0x3d800000,0xbc483d7b,0xbd6dbcc4,0x3d0ebd55,0xbd353d35,0xbd0ebd55,0x3d6dbcc4,0x3c483d7b,0x80003d80,0xbd7bbc48,0x3cc4bd6d,0x3d553d0e,
0x3d800000,0xbcc43d6d,0xbd35bd35,0x3d6dbcc4,0x80003d80,0xbd6dbcc4,0x3d35bd35,0x3cc43d6d,0xbd800000,0x3cc4bd6d,0x3d353d35,0xbd6d3cc4,0x8000bd80,0x3d6d3cc4,0xbd353d35,0xbcc4bd6d,
0x3d800000,0xbcc43d6d,0xbd35bd35,0x3d6dbcc4,0x80003d80,0xbd6dbcc4,0x3d35bd35,0x3cc43d6d,0xbd800000,0x3cc4bd6d,0x3d353d35,0xbd6d3cc4,0x8000bd80,0x3d6d3cc4,0xbd353d35,0xbcc4bd6d,
0xbd35bd35,0x3d7bbc48,0xbcc43d6d,0xbd0ebd55,0x80003d80,0xbd55bd0e,0x3d6dbcc4,0xbc483d7b,0x3d35bd35,0x3c483d7b,0xbd6dbcc4,0x3d55bd0e,0xbd800000,0x3d0ebd55,0x3cc43d6d,0xbd7bbc48,
0x3d353d35,0xbd7b3c48,0x3cc4bd6d,0x3d0e3d55,0x8000bd80,0x3d553d0e,0xbd6d3cc4,0x3c48bd7b,0xbd353d35,0xbc48bd7b,0x3d6d3cc4,0xbd553d0e,0x3d800000,0xbd0e3d55,0xbcc4bd6d,0x3d7b3c48,
0xbd800000,0x3d35bd35,0x80003d80,0xbd35bd35,0x3d800000,0xbd353d35,0x8000bd80,0x3d353d35,0xbd800000,0x3d35bd35,0x80003d80,0xbd35bd35,0x3d800000,0xbd353d35,0x8000bd80,0x3d353d35,
0xbd800000,0x3d35bd35,0x80003d80,0xbd35bd35,0x3d800000,0xbd353d35,0x8000bd80,0x3d353d35,0xbd800000,0x3d35bd35,0x80003d80,0xbd35bd35,0x3d800000,0xbd353d35,0x8000bd80,0x3d353d35,
0xbd35bd35,0x3d7b3c48,0xbd6d3cc4,0x3d0ebd55,0x3d800000,0xbd553d0e,0x3cc4bd6d,0x3c483d7b,0x3d35bd35,0xbc483d7b,0xbcc4bd6d,0x3d553d0e,0x80003d80,0xbd0ebd55,0x3d6d3cc4,0xbd7b3c48,
0x3d353d35,0xbd7bbc48,0x3d6dbcc4,0xbd0e3d55,0xbd800000,0x3d55bd0e,0xbcc43d6d,0xbc48bd7b,0xbd353d35,0x3c48bd7b,0x3cc43d6d,0xbd55bd0e,0x8000bd80,0x3d0e3d55,0xbd6dbcc4,0x3d7bbc48,
0x3d800000,0xbd6d3cc4,0x3d35bd35,0xbcc43d6d,0x8000bd80,0x3cc43d6d,0xbd35bd35,0x3d6d3cc4,0xbd800000,0x3d6dbcc4,0xbd353d35,0x3cc4bd6d,0x80003d80,0xbcc4bd6d,0x3d353d35,0xbd6dbcc4,
0x3d800000,0xbd6d3cc4,0x3d35bd35,0xbcc43d6d,0x8000bd80,0x3cc43d6d,0xbd35bd35,0x3d6d3cc4,0xbd800000,0x3d6dbcc4,0xbd353d35,0x3cc4bd6d,0x80003d80,0xbcc4bd6d,0x3d353d35,0xbd6dbcc4,
0xbd35bd35,0x3d553d0e,0xbd6dbcc4,0x3d7b3c48,0x8000bd80,0x3c483d7b,0xbcc4bd6d,0x3d0e3d55,0x3d35bd35,0xbd0e3d55,0x3cc4bd6d,0xbc483d7b,0x3d800000,0xbd7b3c48,0x3d6dbcc4,0xbd553d0e,
0x3d353d35,0xbd55bd0e,0x3d6d3cc4,0xbd7bbc48,0x80003d80,0xbc48bd7b,0x3cc43d6d,0xbd0ebd55,0xbd353d35,0x3d0ebd55,0xbcc43d6d,0x3c48bd7b,0xbd800000,0x3d7bbc48,0xbd6d3cc4,0x3d55bd0e,
0x3d80,0xbd80,0x3d80,0xbd80,0x3d80,0xbd80,0x3d80,0xbd80,0x3d80,0xbd80,0x3d80,0xbd80,0x3d80,0xbd80,0x3d80,0xbd80,
0x3d80,0xbd80,0x3d80,0xbd80,0x3d80,0xbd80,0x3d80,0xbd80,0x3d80,0xbd80,0x3d80,0xbd80,0x3d80,0xbd80,0x3d80,0xbd80,
0xbd353d35,0x3d55bd0e,0xbd6d3cc4,0x3d7bbc48,0x3d80,0x3c48bd7b,0xbcc43d6d,0x3d0ebd55,0xbd35bd35,0x3d0e3d55,0xbcc4bd6d,0x3c483d7b,0xbd800000,0x3d7b3c48,0xbd6dbcc4,0x3d553d0e,
0x3d35bd35,0xbd553d0e,0x3d6dbcc4,0xbd7b3c48,0xbd80,0xbc483d7b,0x3cc4bd6d,0xbd0e3d55,0x3d353d35,0xbd0ebd55,0x3cc43d6d,0xbc48bd7b,0x3d800000,0xbd7bbc48,0x3d6d3cc4,0xbd55bd0e,
0xbd80,0xbcc43d6d,0x3d35bd35,0xbd6d3cc4,0x3d800000,0xbd6dbcc4,0x3d353d35,0xbcc4bd6d,0x3d80,0x3cc4bd6d,0xbd353d35,0x3d6dbcc4,0xbd800000,0x3d6d3cc4,0xbd35bd35,0x3cc43d6d,
0xbd80,0xbcc43d6d,0x3d35bd35,0xbd6d3cc4,0x3d800000,0xbd6dbcc4,0x3d353d35,0xbcc4bd6d,0x3d80,0x3cc4bd6d,0xbd353d35,0x3d6dbcc4,0xbd800000,0x3d6d3cc4,0xbd35bd35,0x3cc43d6d,
0xbd353d35,0x3d7bbc48,0xbd6dbcc4,0x3d0e3d55,0x3d800000,0xbd55bd0e,0x3cc43d6d,0x3c48bd7b,0xbd35bd35,0x3c483d7b,0x3cc4bd6d,0xbd553d0e,0x3d80,0x3d0ebd55,0xbd6d3cc4,0x3d7b3c48,
0x3d35bd35,0xbd7b3c48,0x3d6d3cc4,0xbd0ebd55,0xbd800000,0x3d553d0e,0xbcc4bd6d,0xbc483d7b,0x3d353d35,0xbc48bd7b,0xbcc43d6d,0x3d55bd0e,0xbd80,0xbd0e3d55,0x3d6dbcc4,0xbd7bbc48,
0x3d80,0x3d35bd35,0xbd800000,0x3d353d35,0xbd80,0xbd353d35,0x3d800000,0xbd35bd35,0x3d80,0x3d35bd35,0xbd800000,0x3d353d35,0xbd80,0xbd353d35,0x3d800000,0xbd35bd35,
0x3d80,0x3d35bd35,0xbd800000,0x3d353d35,0xbd80,0xbd353d35,0x3d800000,0xbd35bd35,0x3d80,0x3d35bd35,0xbd800000,0x3d353d35,0xbd80,0xbd353d35,0x3d800000,0xbd35bd35,
0xbd353d35,0x3d7b3c48,0xbcc4bd6d,0xbd0e3d55,0xbd80,0xbd553d0e,0x3d6d3cc4,0xbc48bd7b,0xbd35bd35,0xbc483d7b,0x3d6dbcc4,0xbd55bd0e,0x3d800000,0xbd0ebd55,0xbcc43d6d,0x3d7bbc48,
0x3d35bd35,0xbd7bbc48,0x3cc43d6d,0x3d0ebd55,0x3d80,0x3d55bd0e,0xbd6dbcc4,0x3c483d7b,0x3d353d35,0x3c48bd7b,0xbd6d3cc4,0x3d553d0e,0xbd800000,0x3d0e3d55,0x3cc4bd6d,0xbd7b3c48,
0xbd80,0xbd6d3cc4,0x3d353d35,0x3cc4bd6d,0xbd800000,0x3cc43d6d,0x3d35bd35,0xbd6dbcc4,0x3d80,0x3d6dbcc4,0xbd35bd35,0xbcc43d6d,0x3d800000,0xbcc4bd6d,0xbd353d35,0x3d6d3cc4,
0xbd80,0xbd6d3cc4,0x3d353d35,0x3cc4bd6d,0xbd800000,0x3cc43d6d,0x3d35bd35,0xbd6dbcc4,0x3d80,0x3d6dbcc4,0xbd35bd35,0xbcc43d6d,0x3d800000,0xbcc4bd6d,0xbd353d35,0x3d6d3cc4,
0xbd353d35,0x3d553d0e,0x3cc4bd6d,0xbd7bbc48,0xbd800000,0x3c483d7b,0x3d6dbcc4,0xbd0ebd55,0xbd35bd35,0xbd0e3d55,0x3d6d3cc4,0x3c48bd7b,0xbd80,0xbd7b3c48,0x3cc43d6d,0x3d55bd0e,
0x3d35bd35,0xbd55bd0e,0xbcc43d6d,0x3d7b3c48,0x3d800000,0xbc48bd7b,0xbd6d3cc4,0x3d0e3d55,0x3d353d35,0x3d0ebd55,0xbd6dbcc4,0xbc483d7b,0x3d80,0x3d7bbc48,0xbcc4bd6d,0xbd553d0e,
0xbd800000,0x3d800000,0xbd800000,0x3d800000,0xbd800000,0x3d800000,0xbd800000,0x3d800000,0xbd800000,0x3d800000,0xbd800000,0x3d800000,0xbd800000,0x3d800000,0xbd800000,0x3d800000,
0xbd800000,0x3d800000,0xbd800000,0x3d800000,0xbd800000,0x3d800000,0xbd800000,0x3d800000,0xbd800000,0x3d800000,0xbd800000,0x3d800000,0xbd800000,0x3d800000,0xbd800000,0x3d800000,
0xbd35bd35,0x3d0e3d55,0xbcc4bd6d,0x3c483d7b,0xbd800000,0x3d7b3c48,0xbd6dbcc4,0x3d553d0e,0x3d35bd35,0xbd553d0e,0x3d6dbcc4,0xbd7b3c48,0x8000bd80,0xbc483d7b,0x3cc4bd6d,0xbd0e3d55,
0x3d353d35,0xbd0ebd55,0x3cc43d6d,0xbc48bd7b,0x3d800000,0xbd7bbc48,0x3d6d3cc4,0xbd55bd0e,0xbd353d35,0x3d55bd0e,0xbd6d3cc4,0x3d7bbc48,0x80003d80,0x3c48bd7b,0xbcc43d6d,0x3d0ebd55,
0x3d800000,0xbd6dbcc4,0x3d353d35,0xbcc4bd6d,0x80003d80,0x3cc4bd6d,0xbd353d35,0x3d6dbcc4,0xbd800000,0x3d6d3cc4,0xbd35bd35,0x3cc43d6d,0x8000bd80,0xbcc43d6d,0x3d35bd35,0xbd6d3cc4,
0x3d800000,0xbd6dbcc4,0x3d353d35,0xbcc4bd6d,0x80003d80,0x3cc4bd6d,0xbd353d35,0x3d6dbcc4,0xbd800000,0x3d6d3cc4,0xbd35bd35,0x3cc43d6d,0x8000bd80,0xbcc43d6d,0x3d35bd35,0xbd6d3cc4,
0xbd35bd35,0x3c483d7b,0x3cc4bd6d,0xbd553d0e,0x80003d80,0x3d0ebd55,0xbd6d3cc4,0x3d7b3c48,0x3d35bd35,0xbd7b3c48,0x3d6d3cc4,0xbd0ebd55,0xbd800000,0x3d553d0e,0xbcc4bd6d,0xbc483d7b,
0x3d353d35,0xbc48bd7b,0xbcc43d6d,0x3d55bd0e,0x8000bd80,0xbd0e3d55,0x3d6dbcc4,0xbd7bbc48,0xbd353d35,0x3d7bbc48,0xbd6dbcc4,0x3d0e3d55,0x3d800000,0xbd55bd0e,0x3cc43d6d,0x3c48bd7b,
0xbd800000,0x3d353d35,0x8000bd80,0xbd353d35,0x3d800000,0xbd35bd35,0x80003d80,0x3d35bd35,0xbd800000,0x3d353d35,0x8000bd80,0xbd353d35,0x3d800000,0xbd35bd35,0x80003d80,0x3d35bd35,
0xbd800000,0x3d353d35,0x8000bd80,0xbd353d35,0x3d800000,0xbd35bd35,0x80003d80,0x3d35bd35,0xbd800000,0x3d353d35,0x8000bd80,0xbd353d35,0x3d800000,0xbd35bd35,0x80003d80,0x3d35bd35,
0xbd35bd35,0xbc483d7b,0x3d6dbcc4,0xbd55bd0e,0x3d800000,0xbd0ebd55,0xbcc43d6d,0x3d7bbc48,0x3d35bd35,0xbd7bbc48,0x3cc43d6d,0x3d0ebd55,0x80003d80,0x3d55bd0e,0xbd6dbcc4,0x3c483d7b,
0x3d353d35,0x3c48bd7b,0xbd6d3cc4,0x3d553d0e,0xbd800000,0x3d0e3d55,0x3cc4bd6d,0xbd7b3c48,0xbd353d35,0x3d7b3c48,0xbcc4bd6d,0xbd0e3d55,0x8000bd80,0xbd553d0e,0x3d6d3cc4,0xbc48bd7b,
0x3d800000,0xbcc4bd6d,0xbd353d35,0x3d6d3cc4,0x8000bd80,0xbd6d3cc4,0x3d353d35,0x3cc4bd6d,0xbd800000,0x3cc43d6d,0x3d35bd35,0xbd6dbcc4,0x80003d80,0x3d6dbcc4,0xbd35bd35,0xbcc43d6d,
0x3d800000,0xbcc4bd6d,0xbd353d35,0x3d6d3cc4,0x8000bd80,0xbd6d3cc4,0x3d353d35,0x3cc4bd6d,0xbd800000,0x3cc43d6d,0x3d35bd35,0xbd6dbcc4,0x80003d80,0x3d6dbcc4,0xbd35bd35,0xbcc43d6d,
0xbd35bd35,0xbd0e3d55,0x3d6d3cc4,0x3c48bd7b,0x8000bd80,0xbd7b3c48,0x3cc43d6d,0x3d55bd0e,0x3d35bd35,0xbd55bd0e,0xbcc43d6d,0x3d7b3c48,0x3d800000,0xbc48bd7b,0xbd6d3cc4,0x3d0e3d55,
0x3d353d35,0x3d0ebd55,0xbd6dbcc4,0xbc483d7b,0x80003d80,0x3d7bbc48,0xbcc4bd6d,0xbd553d0e,0xbd353d35,0x3d553d0e,0x3cc4bd6d,0xbd7bbc48,0xbd800000,0x3c483d7b,0x3d6dbcc4,0xbd0ebd55,
0x3d80,0x3d800000,0xbd80,0xbd800000,0x3d80,0x3d800000,0xbd80,0xbd800000,0x3d80,0x3d800000,0xbd80,0xbd800000,0x3d80,0x3d800000,0xbd80,0xbd800000,
0x3d80,0x3d800000,0xbd80,0xbd800000,0x3d80,0x3d800000,0xbd80,0xbd800000,0x3d80,0x3d800000,0xbd80,0xbd800000,0x3d80,0x3d800000,0xbd80,0xbd800000,
0xbd353d35,0x3d0e3d55,0x3d6dbcc4,0xbc48bd7b,0x3d80,0x3d7b3c48,0x3cc4bd6d,0xbd55bd0e,0xbd35bd35,0xbd553d0e,0x3cc43d6d,0x3d7bbc48,0xbd800000,0xbc483d7b,0x3d6d3cc4,0x3d0ebd55,
0x3d35bd35,0xbd0ebd55,0xbd6d3cc4,0x3c483d7b,0xbd80,0xbd7bbc48,0xbcc43d6d,0x3d553d0e,0x3d353d35,0x3d55bd0e,0xbcc4bd6d,0xbd7b3c48,0x3d800000,0x3c48bd7b,0xbd6dbcc4,0xbd0e3d55,
0xbd80,0xbd6dbcc4,0xbd353d35,0x3cc43d6d,0x3d800000,0x3cc4bd6d,0xbd35bd35,0xbd6d3cc4,0x3d80,0x3d6d3cc4,0x3d35bd35,0xbcc4bd6d,0xbd800000,0xbcc43d6d,0x3d353d35,0x3d6dbcc4,
0xbd80,0xbd6dbcc4,0xbd353d35,0x3cc43d6d,0x3d800000,0x3cc4bd6d,0xbd35bd35,0xbd6d3cc4,0x3d80,0x3d6d3cc4,0x3d35bd35,0xbcc4bd6d,0xbd800000,0xbcc43d6d,0x3d353d35,0x3d6dbcc4,
0xbd353d35,0x3c483d7b,0x3d6d3cc4,0x3d55bd0e,0x3d800000,0x3d0ebd55,0xbcc4bd6d,0xbd7bbc48,0xbd35bd35,0xbd7b3c48,0xbcc43d6d,0x3d0e3d55,0x3d80,0x3d553d0e,0x3d6dbcc4,0x3c48bd7b,
0x3d35bd35,0xbc48bd7b,0xbd6dbcc4,0xbd553d0e,0xbd800000,0xbd0e3d55,0x3cc43d6d,0x3d7b3c48,0x3d353d35,0x3d7bbc48,0x3cc4bd6d,0xbd0ebd55,0xbd80,0xbd55bd0e,0xbd6d3cc4,0xbc483d7b,
0x3d80,0x3d353d35,0x3d800000,0x3d35bd35,0xbd80,0xbd35bd35,0xbd800000,0xbd353d35,0x3d80,0x3d353d35,0x3d800000,0x3d35bd35,0xbd80,0xbd35bd35,0xbd800000,0xbd353d35,
0x3d80,0x3d353d35,0x3d800000,0x3d35bd35,0xbd80,0xbd35bd35,0xbd800000,0xbd353d35,0x3d80,0x3d353d35,0x3d800000,0x3d35bd35,0xbd80,0xbd35bd35,0xbd800000,0xbd353d35,
0xbd353d35,0xbc483d7b,0x3cc43d6d,0x3d553d0e,0xbd80,0xbd0ebd55,0xbd6dbcc4,0xbd7b3c48,0xbd35bd35,0xbd7bbc48,0xbd6d3cc4,0xbd0e3d55,0x3d800000,0x3d55bd0e,0x3cc4bd6d,0xbc48bd7b,
0x3d35bd35,0x3c48bd7b,0xbcc4bd6d,0xbd55bd0e,0x3d80,0x3d0e3d55,0x3d6d3cc4,0x3d7bbc48,0x3d353d35,0x3d7b3c48,0x3d6dbcc4,0x3d0ebd55,0xbd800000,0xbd553d0e,0xbcc43d6d,0x3c483d7b,
0xbd80,0xbcc4bd6d,0xbd35bd35,0xbd6dbcc4,0xbd800000,0xbd6d3cc4,0xbd353d35,0xbcc43d6d,0x3d80,0x3cc43d6d,0x3d353d35,0x3d6d3cc4,0x3d800000,0x3d6dbcc4,0x3d35bd35,0x3cc4bd6d,
0xbd80,0xbcc4bd6d,0xbd35bd35,0xbd6dbcc4,0xbd800000,0xbd6d3cc4,0xbd353d35,0xbcc43d6d,0x3d80,0x3cc43d6d,0x3d353d35,0x3d6d3cc4,0x3d800000,0x3d6dbcc4,0x3d35bd35,0x3cc4bd6d,
0xbd353d35,0xbd0e3d55,0xbcc43d6d,0xbc483d7b,0xbd800000,0xbd7b3c48,0xbd6d3cc4,0xbd553d0e,0xbd35bd35,0xbd55bd0e,0xbd6dbcc4,0xbd7bbc48,0xbd80,0xbc48bd7b,0xbcc4bd6d,0xbd0ebd55,
0x3d35bd35,0x3d0ebd55,0x3cc4bd6d,0x3c48bd7b,0x3d800000,0x3d7bbc48,0x3d6dbcc4,0x3d55bd0e,0x3d353d35,0x3d553d0e,0x3d6d3cc4,0x3d7b3c48,0x3d80,0x3c483d7b,0x3cc43d6d,0x3d0e3d55,
0xbd800000,0x80003d80,0x3d800000,0x8000bd80,0xbd800000,0x80003d80,0x3d800000,0x8000bd80,0xbd800000,0x80003d80,0x3d800000,0x8000bd80,0xbd800000,0x80003d80,0x3d800000,0x8000bd80,
0xbd800000,0x80003d80,0x3d800000,0x8000bd80,0xbd800000,0x80003d80,0x3d800000,0x8000bd80,0xbd800000,0x80003d80,0x3d800000,0x8000bd80,0xbd800000,0x80003d80,0x3d800000,0x8000bd80,
0xbd35bd35,0xbd553d0e,0x3cc43d6d,0x3d7bbc48,0xbd800000,0xbc483d7b,0x3d6d3cc4,0x3d0ebd55,0x3d35bd35,0xbd0ebd55,0xbd6d3cc4,0x3c483d7b,0x8000bd80,0xbd7bbc48,0xbcc43d6d,0x3d553d0e,
0x3d353d35,0x3d55bd0e,0xbcc4bd6d,0xbd7b3c48,0x3d800000,0x3c48bd7b,0xbd6dbcc4,0xbd0e3d55,0xbd353d35,0x3d0e3d55,0x3d6dbcc4,0xbc48bd7b,0x80003d80,0x3d7b3c48,0x3cc4bd6d,0xbd55bd0e,
0x3d800000,0x3cc4bd6d,0xbd35bd35,0xbd6d3cc4,0x80003d80,0x3d6d3cc4,0x3d35bd35,0xbcc4bd6d,0xbd800000,0xbcc43d6d,0x3d353d35,0x3d6dbcc4,0x8000bd80,0xbd6dbcc4,0xbd353d35,0x3cc43d6d,
0x3d800000,0x3cc4bd6d,0xbd35bd35,0xbd6d3cc4,0x80003d80,0x3d6d3cc4,0x3d35bd35,0xbcc4bd6d,0xbd800000,0xbcc43d6d,0x3d353d35,0x3d6dbcc4,0x8000bd80,0xbd6dbcc4,0xbd353d35,0x3cc43d6d,
0xbd35bd35,0xbd7b3c48,0xbcc43d6d,0x3d0e3d55,0x80003d80,0x3d553d0e,0x3d6dbcc4,0x3c48bd7b,0x3d35bd35,0xbc48bd7b,0xbd6dbcc4,0xbd553d0e,0xbd800000,0xbd0e3d55,0x3cc43d6d,0x3d7b3c48,
0x3d353d35,0x3d7bbc48,0x3cc4bd6d,0xbd0ebd55,0x8000bd80,0xbd55bd0e,0xbd6d3cc4,0xbc483d7b,0xbd353d35,0x3c483d7b,0x3d6d3cc4,0x3d55bd0e,0x3d800000,0x3d0ebd55,0xbcc4bd6d,0xbd7bbc48,
0xbd800000,0xbd353d35,0x80003d80,0x3d353d35,0x3d800000,0x3d35bd35,0x8000bd80,0xbd35bd35,0xbd800000,0xbd353d35,0x80003d80,0x3d353d35,0x3d800000,0x3d35bd35,0x8000bd80,0xbd35bd35,
0xbd800000,0xbd353d35,0x80003d80,0x3d353d35,0x3d800000,0x3d35bd35,0x8000bd80,0xbd35bd35,0xbd800000,0xbd353d35,0x80003d80,0x3d353d35,0x3d800000,0x3d35bd35,0x8000bd80,0xbd35bd35,
0xbd35bd35,0xbd7bbc48,0xbd6d3cc4,0xbd0e3d55,0x3d800000,0x3d55bd0e,0x3cc4bd6d,0xbc48bd7b,0x3d35bd35,0x3c48bd7b,0xbcc4bd6d,0xbd55bd0e,0x80003d80,0x3d0e3d55,0x3d6d3cc4,0x3d7bbc48,
0x3d353d35,0x3d7b3c48,0x3d6dbcc4,0x3d0ebd55,0xbd800000,0xbd553d0e,0xbcc43d6d,0x3c483d7b,0xbd353d35,0xbc483d7b,0x3cc43d6d,0x3d553d0e,0x8000bd80,0xbd0ebd55,0xbd6dbcc4,0xbd7b3c48,
0x3d800000,0x3d6dbcc4,0x3d35bd35,0x3cc4bd6d,0x8000bd80,0xbcc4bd6d,0xbd35bd35,0xbd6dbcc4,0xbd800000,0xbd6d3cc4,0xbd353d35,0xbcc43d6d,0x80003d80,0x3cc43d6d,0x3d353d35,0x3d6d3cc4,
0x3d800000,0x3d6dbcc4,0x3d35bd35,0x3cc4bd6d,0x8000bd80,0xbcc4bd6d,0xbd35bd35,0xbd6dbcc4,0xbd800000,0xbd6d3cc4,0xbd353d35,0xbcc43d6d,0x80003d80,0x3cc43d6d,0x3d353d35,0x3d6d3cc4,
0xbd35bd35,0xbd55bd0e,0xbd6dbcc4,0xbd7bbc48,0x8000bd80,0xbc48bd7b,0xbcc4bd6d,0xbd0ebd55,0x3d35bd35,0x3d0ebd55,0x3cc4bd6d,0x3c48bd7b,0x3d800000,0x3d7bbc48,0x3d6dbcc4,0x3d55bd0e,
0x3d353d35,0x3d553d0e,0x3d6d3cc4,0x3d7b3c48,0x80003d80,0x3c483d7b,0x3cc43d6d,0x3d0e3d55,0xbd353d35,0xbd0e3d55,0xbcc43d6d,0xbc483d7b,0xbd800000,0xbd7b3c48,0xbd6d3cc4,0xbd553d0e,
0x3d80,0xbb493d80,0xbbc93d7f,0xbc163d7d,0xbc483d7b,0xbc793d78,0xbc953d75,0xbcac3d71,0xbcc43d6d,0xbcdb3d67,0xbcf13d62,0xbd043d5c,0xbd0e3d55,0xbd183d4e,0xbd223d46,0xbd2c3d3e,
0xbd353d35,0xbd3e3d2c,0xbd463d22,0xbd4e3d18,0xbd553d0e,0xbd5c3d04,0xbd623cf1,0xbd673cdb,0xbd6d3cc4,0xbd713cac,0xbd753c95,0xbd783c79,0xbd7b3c48,0xbd7d3c16,0xbd7f3bc9,0xbd803b49,
0xbd553d0e,0xbd713cac,0xbd7f3bc9,0xbd7dbc16,0x3d80,0xbc793d78,0xbcf13d62,0xbd2c3d3e,0xbc48bd7b,0x3b49bd80,0x3c95bd75,0x3d04bd5c,0xbd6dbcc4,0xbd4ebd18,0xbd22bd46,0xbcdbbd67,
0x3d7b3c48,0x3d673cdb,0x3d463d22,0x3d183d4e,0x3d35bd35,0x3d5cbd04,0x3d75bc95,0x3d80bb49,0xbd0e3d55,0xbd3e3d2c,0xbd623cf1,0xbd783c79,0x3cc43d6d,0x3c163d7d,0xbbc93d7f,0xbcac3d71,
0x3cc4bd6d,0x3d3ebd2c,0x3d75bc95,0x3d7d3c16,0x3d553d0e,0x3d043d5c,0x3bc93d7f,0xbcac3d71,0x3d80,0xbcdb3d67,0xbd463d22,0xbd783c79,0xbd7bbc48,0xbd4ebd18,0xbcf1bd62,0xbb49bd80,
0x3d6dbcc4,0x3d803b49,0x3d623cf1,0x3d183d4e,0x3c483d7b,0xbc793d78,0xbd223d46,0xbd673cdb,0xbd353d35,0xbd713cac,0xbd7fbbc9,0xbd5cbd04,0xbd0ebd55,0xbc16bd7d,0x3c95bd75,0x3d2cbd3e,
0xbd7b3c48,0xbd67bcdb,0xbcf1bd62,0x3c16bd7d,0x3d6d3cc4,0x3d043d5c,0xbbc93d7f,0xbd2c3d3e,0xbd0ebd55,0x3b49bd80,0x3d22bd46,0x3d78bc79,0x3d80,0xbd183d4e,0xbd753c95,0xbd71bcac,
0x3d553d0e,0x3cac3d71,0xbc953d75,0xbd4e3d18,0xbcc4bd6d,0x3c79bd78,0x3d46bd22,0x3d80bb49,0xbc483d7b,0xbd3e3d2c,0xbd7f3bc9,0xbd5cbd04,0x3d35bd35,0x3d7dbc16,0x3d623cf1,0x3cdb3d67,
0xbd353d35,0xbd80bb49,0xbd22bd46,0x3c16bd7d,0x3d55bd0e,0x3d783c79,0x3cf13d62,0xbcac3d71,0xbd6d3cc4,0xbd67bcdb,0xbc95bd75,0x3d04bd5c,0x3d7bbc48,0x3d4e3d18,0x3bc93d7f,0xbd2c3d3e,
0x3d80,0xbd3e3d2c,0xbd7fbbc9,0xbd18bd4e,0x3c48bd7b,0x3d5cbd04,0x3d753c95,0x3cdb3d67,0xbcc43d6d,0xbd713cac,0xbd62bcf1,0xbc79bd78,0x3d0ebd55,0x3d7dbc16,0x3d463d22,0x3b493d80,
0xbd7bbc48,0xbcacbd71,0x3d22bd46,0x3d7d3c16,0x3d35bd35,0x3d783c79,0x3c953d75,0xbd2c3d3e,0x3d0ebd55,0x3d803b49,0x3cf13d62,0xbd043d5c,0x3cc43d6d,0xbd183d4e,0xbd7fbbc9,0xbcdbbd67,
0x3d55bd0e,0x3d673cdb,0x3bc93d7f,0xbd4e3d18,0x3d80,0xbd5c3d04,0xbd62bcf1,0xbb49bd80,0x3c483d7b,0xbd3e3d2c,0xbd75bc95,0xbc79bd78,0xbd6dbcc4,0xbc16bd7d,0x3d46bd22,0x3d713cac,
0x3d6dbcc4,0x3d2c3d3e,0xbcf13d62,0xbd7dbc16,0xbc48bd7b,0x3d5cbd04,0x3d463d22,0xbcac3d71,0xbd353d35,0xbd67bcdb,0x3bc9bd7f,0x3d78bc79,0x3d0e3d55,0xbd183d4e,0xbd75bc95,0xbb49bd80,
0x3cc4bd6d,0x3d803b49,0x3c953d75,0xbd4e3d18,0xbd55bd0e,0x3c79bd78,0x3d7fbbc9,0x3cdb3d67,0x3d80,0xbd713cac,0xbd22bd46,0x3d04bd5c,0x3d7b3c48,0x3c163d7d,0xbd623cf1,0xbd3ebd2c,
0xbd55bd0e,0x3cdbbd67,0x3d753c95,0xbc163d7d,0xbcc4bd6d,0x3d5cbd04,0x3d223d46,0xbd2c3d3e,0x3c48bd7b,0x3d803b49,0x3bc93d7f,0xbd783c79,0x3d35bd35,0x3d4e3d18,0xbcf13d62,0xbd71bcac,
0x3d7bbc48,0x3cac3d71,0xbd623cf1,0xbd18bd4e,0x3d6d3cc4,0xbc793d78,0xbd7fbbc9,0xbb49bd80,0x3d0e3d55,0xbd3e3d2c,0xbd46bd22,0x3d04bd5c,0x3d80,0xbd7d3c16,0xbc95bd75,0x3d67bcdb,
0xbd800000,0xbd80bb49,0xbd7fbbc9,0xbd7dbc16,0xbd7bbc48,0xbd78bc79,0xbd75bc95,0xbd71bcac,0xbd6dbcc4,0xbd67bcdb,0xbd62bcf1,0xbd5cbd04,0xbd55bd0e,0xbd4ebd18,0xbd46bd22,0xbd3ebd2c,
0xbd35bd35,0xbd2cbd3e,0xbd22bd46,0xbd18bd4e,0xbd0ebd55,0xbd04bd5c,0xbcf1bd62,0xbcdbbd67,0xbcc4bd6d,0xbcacbd71,0xbc95bd75,0xbc79bd78,0xbc48bd7b,0xbc16bd7d,0xbbc9bd7f,0xbb49bd80,
0xbd0ebd55,0xbcacbd71,0xbbc9bd7f,0x3c16bd7d,0xbd800000,0xbd78bc79,0xbd62bcf1,0xbd3ebd2c,0x3d7bbc48,0x3d803b49,0x3d753c95,0x3d5c3d04,0x3cc4bd6d,0x3d18bd4e,0x3d46bd22,0x3d67bcdb,
0xbc483d7b,0xbcdb3d67,0xbd223d46,0xbd4e3d18,0x3d353d35,0x3d043d5c,0x3c953d75,0x3b493d80,0xbd55bd0e,0xbd2cbd3e,0xbcf1bd62,0xbc79bd78,0xbd6d3cc4,0xbd7d3c16,0xbd7fbbc9,0xbd71bcac,
0x3d6d3cc4,0x3d2c3d3e,0x3c953d75,0xbc163d7d,0xbd0e3d55,0xbd5c3d04,0xbd7f3bc9,0xbd71bcac,0xbd800000,0xbd67bcdb,0xbd22bd46,0xbc79bd78,0x3c48bd7b,0x3d18bd4e,0x3d62bcf1,0x3d80bb49,
0x3cc43d6d,0xbb493d80,0xbcf13d62,0xbd4e3d18,0xbd7b3c48,0xbd78bc79,0xbd46bd22,0xbcdbbd67,0xbd35bd35,0xbcacbd71,0x3bc9bd7f,0x3d04bd5c,0x3d55bd0e,0x3d7dbc16,0x3d753c95,0x3d3e3d2c,
0xbc48bd7b,0x3cdbbd67,0x3d62bcf1,0x3d7d3c16,0xbcc43d6d,0xbd5c3d04,0xbd7fbbc9,0xbd3ebd2c,0x3d55bd0e,0x3d803b49,0x3d463d22,0x3c793d78,0xbd800000,0xbd4ebd18,0xbc95bd75,0x3cacbd71,
0xbd0e3d55,0xbd713cac,0xbd75bc95,0xbd18bd4e,0x3d6dbcc4,0x3d783c79,0x3d223d46,0x3b493d80,0xbd7bbc48,0xbd2cbd3e,0xbbc9bd7f,0x3d04bd5c,0x3d353d35,0x3c163d7d,0xbcf13d62,0xbd673cdb,
0xbd35bd35,0x3b49bd80,0x3d46bd22,0x3d7d3c16,0x3d0e3d55,0xbc793d78,0xbd623cf1,0xbd71bcac,0xbcc4bd6d,0x3cdbbd67,0x3d75bc95,0x3d5c3d04,0x3c483d7b,0xbd183d4e,0xbd7f3bc9,0xbd3ebd2c,
0xbd800000,0xbd2cbd3e,0x3bc9bd7f,0x3d4ebd18,0x3d7b3c48,0x3d043d5c,0xbc953d75,0xbd673cdb,0xbd6dbcc4,0xbcacbd71,0x3cf1bd62,0x3d78bc79,0x3d553d0e,0x3c163d7d,0xbd223d46,0xbd803b49,
0x3c48bd7b,0x3d71bcac,0x3d463d22,0xbc163d7d,0x3d353d35,0xbc793d78,0xbd753c95,0xbd3ebd2c,0x3d553d0e,0xbb493d80,0xbd623cf1,0xbd5cbd04,0xbd6d3cc4,0xbd4ebd18,0x3bc9bd7f,0x3d67bcdb,
0x3d0e3d55,0xbcdb3d67,0xbd7f3bc9,0xbd18bd4e,0xbd800000,0xbd04bd5c,0x3cf1bd62,0x3d80bb49,0xbd7b3c48,0xbd2cbd3e,0x3c95bd75,0x3d78bc79,0x3cc4bd6d,0x3d7dbc16,0x3d223d46,0xbcac3d71,
0x3cc43d6d,0xbd3e3d2c,0xbd62bcf1,0x3c16bd7d,0x3d7bbc48,0x3d043d5c,0xbd223d46,0xbd71bcac,0xbd35bd35,0x3cdbbd67,0x3d7f3bc9,0x3c793d78,0xbd553d0e,0xbd4ebd18,0x3c95bd75,0x3d80bb49,
0x3d6d3cc4,0xbb493d80,0xbd753c95,0xbd18bd4e,0x3d0ebd55,0x3d783c79,0x3bc93d7f,0xbd673cdb,0xbd800000,0xbcacbd71,0x3d46bd22,0x3d5c3d04,0xbc483d7b,0xbd7d3c16,0xbcf1bd62,0x3d2cbd3e,
0x3d0ebd55,0x3d673cdb,0xbc953d75,0xbd7dbc16,0x3d6dbcc4,0x3d043d5c,0xbd463d22,0xbd3ebd2c,0x3d7b3c48,0xbb493d80,0xbd7f3bc9,0xbc79bd78,0x3d353d35,0xbd183d4e,0xbd62bcf1,0x3cacbd71,
0x3c483d7b,0xbd713cac,0xbcf1bd62,0x3d4ebd18,0xbcc43d6d,0xbd78bc79,0x3bc9bd7f,0x3d80bb49,0xbd553d0e,0xbd2cbd3e,0x3d22bd46,0x3d5c3d04,0xbd800000,0xbc16bd7d,0x3d75bc95,0x3cdb3d67,
0x3d80,0xbd80bb49,0x3bc9bd7f,0x3d7d3c16,0xbc483d7b,0xbd78bc79,0x3c95bd75,0x3d713cac,0xbcc43d6d,0xbd67bcdb,0x3cf1bd62,0x3d5c3d04,0xbd0e3d55,0xbd4ebd18,0x3d22bd46,0x3d3e3d2c,
0xbd353d35,0xbd2cbd3e,0x3d46bd22,0x3d183d4e,0xbd553d0e,0xbd04bd5c,0x3d62bcf1,0x3cdb3d67,0xbd6d3cc4,0xbcacbd71,0x3d75bc95,0x3c793d78,0xbd7b3c48,0xbc16bd7d,0x3d7fbbc9,0x3b493d80,
0xbd553d0e,0xbcacbd71,0x3d7fbbc9,0xbc163d7d,0x3d80,0xbd78bc79,0x3cf1bd62,0x3d3e3d2c,0xbc48bd7b,0x3d803b49,0xbc953d75,0xbd5cbd04,0xbd6dbcc4,0x3d18bd4e,0x3d223d46,0xbd673cdb,
0x3d7b3c48,0xbcdb3d67,0xbd46bd22,0x3d4ebd18,0x3d35bd35,0x3d043d5c,0xbd753c95,0xbb49bd80,0xbd0e3d55,0xbd2cbd3e,0x3d62bcf1,0x3c793d78,0x3cc43d6d,0xbd7d3c16,0x3bc9bd7f,0x3d713cac,
0x3cc4bd6d,0x3d2c3d3e,0xbd753c95,0x3c16bd7d,0x3d553d0e,0xbd5c3d04,0xbbc9bd7f,0x3d713cac,0x3d80,0xbd67bcdb,0x3d46bd22,0x3c793d78,0xbd7bbc48,0x3d18bd4e,0x3cf13d62,0xbd803b49,
0x3d6dbcc4,0xbb493d80,0xbd62bcf1,0x3d4ebd18,0x3c483d7b,0xbd78bc79,0x3d22bd46,0x3cdb3d67,0xbd353d35,0xbcacbd71,0x3d7f3bc9,0xbd043d5c,0xbd0ebd55,0x3d7dbc16,0xbc953d75,0xbd3ebd2c,
0xbd7b3c48,0x3cdbbd67,0x3cf13d62,0xbd7dbc16,0x3d6d3cc4,0xbd5c3d04,0x3bc9bd7f,0x3d3e3d2c,0xbd0ebd55,0x3d803b49,0xbd223d46,0xbc79bd78,0x3d80,0xbd4ebd18,0x3d75bc95,0xbcac3d71,
0x3d553d0e,0xbd713cac,0x3c95bd75,0x3d183d4e,0xbcc4bd6d,0x3d783c79,0xbd463d22,0xbb49bd80,0xbc483d7b,0xbd2cbd3e,0x3d7fbbc9,0xbd043d5c,0x3d35bd35,0x3c163d7d,0xbd62bcf1,0x3d67bcdb,
0xbd353d35,0x3b49bd80,0x3d223d46,0xbd7dbc16,0x3d55bd0e,0xbc793d78,0xbcf1bd62,0x3d713cac,0xbd6d3cc4,0x3cdbbd67,0x3c953d75,0xbd5cbd04,0x3d7bbc48,0xbd183d4e,0xbbc9bd7f,0x3d3e3d2c,
0x3d80,0xbd2cbd3e,0x3d7f3bc9,0xbd4e3d18,0x3c48bd7b,0x3d043d5c,0xbd75bc95,0x3d67bcdb,0xbcc43d6d,0xbcacbd71,0x3d623cf1,0xbd783c79,0x3d0ebd55,0x3c163d7d,0xbd46bd22,0x3d80bb49,
0xbd7bbc48,0x3d71bcac,0xbd223d46,0x3c16bd7d,0x3d35bd35,0xbc793d78,0xbc95bd75,0x3d3e3d2c,0x3d0ebd55,0xbb493d80,0xbcf1bd62,0x3d5c3d04,0x3cc43d6d,0xbd4ebd18,0x3d7f3bc9,0xbd673cdb,
0x3d55bd0e,0xbcdb3d67,0xbbc9bd7f,0x3d183d4e,0x3d80,0xbd04bd5c,0x3d623cf1,0xbd803b49,0x3c483d7b,0xbd2cbd3e,0x3d753c95,0xbd783c79,0xbd6dbcc4,0x3d7dbc16,0xbd463d22,0x3cacbd71,
0x3d6dbcc4,0xbd3e3d2c,0x3cf1bd62,0xbc163d7d,0xbc48bd7b,0x3d043d5c,0xbd46bd22,0x3d713cac,0xbd353d35,0x3cdbbd67,0xbbc93d7f,0xbc79bd78,0x3d0e3d55,0xbd4ebd18,0x3d753c95,0xbd803b49,
0x3cc4bd6d,0xbb493d80,0xbc95bd75,0x3d183d4e,0xbd55bd0e,0x3d783c79,0xbd7f3bc9,0x3d67bcdb,0x3d80,0xbcacbd71,0x3d223d46,0xbd5cbd04,0x3d7b3c48,0xbd7d3c16,0x3d62bcf1,0xbd2c3d3e,
0xbd55bd0e,0x3d673cdb,0xbd75bc95,0x3d7d3c16,0xbcc4bd6d,0x3d043d5c,0xbd22bd46,0x3d3e3d2c,0x3c48bd7b,0xbb493d80,0xbbc9bd7f,0x3c793d78,0x3d35bd35,0xbd183d4e,0x3cf1bd62,0xbcac3d71,
0x3d7bbc48,0xbd713cac,0x3d62bcf1,0xbd4e3d18,0x3d6d3cc4,0xbd78bc79,0x3d7f3bc9,0xbd803b49,0x3d0e3d55,0xbd2cbd3e,0x3d463d22,0xbd5cbd04,0x3d80,0xbc16bd7d,0x3c953d75,0xbcdbbd67,
0xbd800000,0x3b49bd80,0x3d7f3bc9,0xbc163d7d,0xbd7bbc48,0x3c79bd78,0x3d753c95,0xbcac3d71,0xbd6dbcc4,0x3cdbbd67,0x3d623cf1,0xbd043d5c,0xbd55bd0e,0x3d18bd4e,0x3d463d22,0xbd2c3d3e,
0xbd35bd35,0x3d3ebd2c,0x3d223d46,0xbd4e3d18,0xbd0ebd55,0x3d5cbd04,0x3cf13d62,0xbd673cdb,0xbcc4bd6d,0x3d71bcac,0x3c953d75,0xbd783c79,0xbc48bd7b,0x3d7dbc16,0x3bc93d7f,0xbd803b49,
0xbd0ebd55,0x3d71bcac,0x3bc93d7f,0xbd7dbc16,0xbd800000,0x3c79bd78,0x3d623cf1,0xbd2c3d3e,0x3d7bbc48,0xbb493d80,0xbd75bc95,0x3d04bd5c,0x3cc4bd6d,0x3d4e3d18,0xbd463d22,0xbcdbbd67,
0xbc483d7b,0xbd67bcdb,0x3d22bd46,0x3d183d4e,0x3d353d35,0xbd5c3d04,0xbc95bd75,0x3d80bb49,0xbd55bd0e,0x3d3ebd2c,0x3cf13d62,0xbd783c79,0xbd6d3cc4,0xbc16bd7d,0x3d7f3bc9,0xbcac3d71,
0x3d6d3cc4,0xbd3e3d2c,0xbc95bd75,0x3d7d3c16,0xbd0e3d55,0xbd04bd5c,0x3d7fbbc9,0xbcac3d71,0xbd800000,0x3cdbbd67,0x3d223d46,0xbd783c79,0x3c48bd7b,0x3d4e3d18,0xbd623cf1,0xbb49bd80,
0x3cc43d6d,0xbd80bb49,0x3cf1bd62,0x3d183d4e,0xbd7b3c48,0x3c79bd78,0x3d463d22,0xbd673cdb,0xbd35bd35,0x3d71bcac,0xbbc93d7f,0xbd5cbd04,0x3d55bd0e,0x3c163d7d,0xbd75bc95,0x3d2cbd3e,
0xbc48bd7b,0x3d673cdb,0xbd623cf1,0x3c16bd7d,0xbcc43d6d,0xbd04bd5c,0x3d7f3bc9,0xbd2c3d3e,0x3d55bd0e,0xbb493d80,0xbd46bd22,0x3d78bc79,0xbd800000,0x3d18bd4e,0x3c953d75,0xbd71bcac,
0xbd0e3d55,0xbcacbd71,0x3d753c95,0xbd4e3d18,0x3d6dbcc4,0xbc793d78,0xbd22bd46,0x3d80bb49,0xbd7bbc48,0x3d3ebd2c,0x3bc93d7f,0xbd5cbd04,0x3d353d35,0xbd7d3c16,0x3cf1bd62,0x3cdb3d67,
0xbd35bd35,0x3d803b49,0xbd463d22,0x3c16bd7d,0x3d0e3d55,0xbd78bc79,0x3d62bcf1,0xbcac3d71,0xbcc4bd6d,0x3d673cdb,0xbd753c95,0x3d04bd5c,0x3c483d7b,0xbd4ebd18,0x3d7fbbc9,0xbd2c3d3e,
0xbd800000,0x3d3ebd2c,0xbbc93d7f,0xbd18bd4e,0x3d7b3c48,0xbd5c3d04,0x3c95bd75,0x3cdb3d67,0xbd6dbcc4,0x3d71bcac,0xbcf13d62,0xbc79bd78,0x3d553d0e,0xbd7d3c16,0x3d22bd46,0x3b493d80,
0x3c48bd7b,0x3cac3d71,0xbd46bd22,0x3d7d3c16,0x3d353d35,0xbd78bc79,0x3d75bc95,0xbd2c3d3e,0x3d553d0e,0xbd80bb49,0x3d62bcf1,0xbd043d5c,0xbd6d3cc4,0x3d18bd4e,0xbbc93d7f,0xbcdbbd67,
0x3d0e3d55,0xbd67bcdb,0x3d7fbbc9,0xbd4e3d18,0xbd800000,0x3d5cbd04,0xbcf13d62,0xbb49bd80,0xbd7b3c48,0x3d3ebd2c,0xbc953d75,0xbc79bd78,0x3cc4bd6d,0x3c163d7d,0xbd22bd46,0x3d713cac,
0x3cc43d6d,0xbd2cbd3e,0x3d623cf1,0xbd7dbc16,0x3d7bbc48,0xbd5c3d04,0x3d22bd46,0xbcac3d71,0xbd35bd35,0x3d673cdb,0xbd7fbbc9,0x3d78bc79,0xbd553d0e,0x3d18bd4e,0xbc953d75,0xbb49bd80,
0x3d6d3cc4,0xbd80bb49,0x3d75bc95,0xbd4e3d18,0x3d0ebd55,0xbc793d78,0xbbc9bd7f,0x3cdb3d67,0xbd800000,0x3d71bcac,0xbd463d22,0x3d04bd5c,0xbc483d7b,0xbc16bd7d,0x3cf13d62,0xbd3ebd2c,
0x3d0ebd55,0xbcdb3d67,0x3c95bd75,0xbc163d7d,0x3d6dbcc4,0xbd5c3d04,0x3d46bd22,0xbd2c3d3e,0x3d7b3c48,0xbd80bb49,0x3d7fbbc9,0xbd783c79,0x3d353d35,0xbd4ebd18,0x3d623cf1,0xbd71bcac,
0x3c483d7b,0xbcacbd71,0x3cf13d62,0xbd18bd4e,0xbcc43d6d,0x3c79bd78,0xbbc93d7f,0xbb49bd80,0xbd553d0e,0x3d3ebd2c,0xbd223d46,0x3d04bd5c,0xbd800000,0x3d7dbc16,0xbd753c95,0x3d67bcdb,
0x3d80,0x3b49bd80,0xbbc93d7f,0x3c16bd7d,0xbc483d7b,0x3c79bd78,0xbc953d75,0x3cacbd71,0xbcc43d6d,0x3cdbbd67,0xbcf13d62,0x3d04bd5c,0xbd0e3d55,0x3d18bd4e,0xbd223d46,0x3d2cbd3e,
0xbd353d35,0x3d3ebd2c,0xbd463d22,0x3d4ebd18,0xbd553d0e,0x3d5cbd04,0xbd623cf1,0x3d67bcdb,0xbd6d3cc4,0x3d71bcac,0xbd753c95,0x3d78bc79,0xbd7b3c48,0x3d7dbc16,0xbd7f3bc9,0x3d80bb49,
0xbd553d0e,0x3d71bcac,0xbd7f3bc9,0x3d7d3c16,0x3d80,0x3c79bd78,0xbcf13d62,0x3d2cbd3e,0xbc48bd7b,0xbb493d80,0x3c95bd75,0xbd043d5c,0xbd6dbcc4,0x3d4e3d18,0xbd22bd46,0x3cdb3d67,
0x3d7b3c48,0xbd67bcdb,0x3d463d22,0xbd18bd4e,0x3d35bd35,0xbd5c3d04,0x3d75bc95,0xbd803b49,0xbd0e3d55,0x3d3ebd2c,0xbd623cf1,0x3d78bc79,0x3cc43d6d,0xbc16bd7d,0xbbc93d7f,0x3cacbd71,
0x3cc4bd6d,0xbd3e3d2c,0x3d75bc95,0xbd7dbc16,0x3d553d0e,0xbd04bd5c,0x3bc93d7f,0x3cacbd71,0x3d80,0x3cdbbd67,0xbd463d22,0x3d78bc79,0xbd7bbc48,0x3d4e3d18,0xbcf1bd62,0x3b493d80,
0x3d6dbcc4,0xbd80bb49,0x3d623cf1,0xbd18bd4e,0x3c483d7b,0x3c79bd78,0xbd223d46,0x3d67bcdb,0xbd353d35,0x3d71bcac,0xbd7fbbc9,0x3d5c3d04,0xbd0ebd55,0x3c163d7d,0x3c95bd75,0xbd2c3d3e,
0xbd7b3c48,0x3d673cdb,0xbcf1bd62,0xbc163d7d,0x3d6d3cc4,0xbd04bd5c,0xbbc93d7f,0x3d2cbd3e,0xbd0ebd55,0xbb493d80,0x3d22bd46,0xbd783c79,0x3d80,0x3d18bd4e,0xbd753c95,0x3d713cac,
0x3d553d0e,0xbcacbd71,0xbc953d75,0x3d4ebd18,0xbcc4bd6d,0xbc793d78,0x3d46bd22,0xbd803b49,0xbc483d7b,0x3d3ebd2c,0xbd7f3bc9,0x3d5c3d04,0x3d35bd35,0xbd7d3c16,0x3d623cf1,0xbcdbbd67,
0xbd353d35,0x3d803b49,0xbd22bd46,0xbc163d7d,0x3d55bd0e,0xbd78bc79,0x3cf13d62,0x3cacbd71,0xbd6d3cc4,0x3d673cdb,0xbc95bd75,0xbd043d5c,0x3d7bbc48,0xbd4ebd18,0x3bc93d7f,0x3d2cbd3e,
0x3d80,0x3d3ebd2c,0xbd7fbbc9,0x3d183d4e,0x3c48bd7b,0xbd5c3d04,0x3d753c95,0xbcdbbd67,0xbcc43d6d,0x3d71bcac,0xbd62bcf1,0x3c793d78,0x3d0ebd55,0xbd7d3c16,0x3d463d22,0xbb49bd80,
0xbd7bbc48,0x3cac3d71,0x3d22bd46,0xbd7dbc16,0x3d35bd35,0xbd78bc79,0x3c953d75,0x3d2cbd3e,0x3d0ebd55,0xbd80bb49,0x3cf13d62,0x3d04bd5c,0x3cc43d6d,0x3d18bd4e,0xbd7fbbc9,0x3cdb3d67,
0x3d55bd0e,0xbd67bcdb,0x3bc93d7f,0x3d4ebd18,0x3d80,0x3d5cbd04,0xbd62bcf1,0x3b493d80,0x3c483d7b,0x3d3ebd2c,0xbd75bc95,0x3c793d78,0xbd6dbcc4,0x3c163d7d,0x3d46bd22,0xbd71bcac,
0x3d6dbcc4,0xbd2cbd3e,0xbcf13d62,0x3d7d3c16,0xbc48bd7b,0xbd5c3d04,0x3d463d22,0x3cacbd71,0xbd353d35,0x3d673cdb,0x3bc9bd7f,0xbd783c79,0x3d0e3d55,0x3d18bd4e,0xbd75bc95,0x3b493d80,
0x3cc4bd6d,0xbd80bb49,0x3c953d75,0x3d4ebd18,0xbd55bd0e,0xbc793d78,0x3d7fbbc9,0xbcdbbd67,0x3d80,0x3d71bcac,0xbd22bd46,0xbd043d5c,0x3d7b3c48,0xbc16bd7d,0xbd623cf1,0x3d3e3d2c,
0xbd55bd0e,0xbcdb3d67,0x3d753c95,0x3c16bd7d,0xbcc4bd6d,0xbd5c3d04,0x3d223d46,0x3d2cbd3e,0x3c48bd7b,0xbd80bb49,0x3bc93d7f,0x3d78bc79,0x3d35bd35,0xbd4ebd18,0xbcf13d62,0x3d713cac,
0x3d7bbc48,0xbcacbd71,0xbd623cf1,0x3d183d4e,0x3d6d3cc4,0x3c79bd78,0xbd7fbbc9,0x3b493d80,0x3d0e3d55,0x3d3ebd2c,0xbd46bd22,0xbd043d5c,0x3d80,0x3d7dbc16,0xbc95bd75,0xbd673cdb,
0xbd800000,0x3d803b49,0xbd7fbbc9,0x3d7d3c16,0xbd7bbc48,0x3d783c79,0xbd75bc95,0x3d713cac,0xbd6dbcc4,0x3d673cdb,0xbd62bcf1,0x3d5c3d04,0xbd55bd0e,0x3d4e3d18,0xbd46bd22,0x3d3e3d2c,
0xbd35bd35,0x3d2c3d3e,0xbd22bd46,0x3d183d4e,0xbd0ebd55,0x3d043d5c,0xbcf1bd62,0x3cdb3d67,0xbcc4bd6d,0x3cac3d71,0xbc95bd75,0x3c793d78,0xbc48bd7b,0x3c163d7d,0xbbc9bd7f,0x3b493d80,
0xbd0ebd55,0x3cac3d71,0xbbc9bd7f,0xbc163d7d,0xbd800000,0x3d783c79,0xbd62bcf1,0x3d3e3d2c,0x3d7bbc48,0xbd80bb49,0x3d753c95,0xbd5cbd04,0x3cc4bd6d,0xbd183d4e,0x3d46bd22,0xbd673cdb,
0xbc483d7b,0x3cdbbd67,0xbd223d46,0x3d4ebd18,0x3d353d35,0xbd04bd5c,0x3c953d75,0xbb49bd80,0xbd55bd0e,0x3d2c3d3e,0xbcf1bd62,0x3c793d78,0xbd6d3cc4,0x3d7dbc16,0xbd7fbbc9,0x3d713cac,
0x3d6d3cc4,0xbd2cbd3e,0x3c953d75,0x3c16bd7d,0xbd0e3d55,0x3d5cbd04,0xbd7f3bc9,0x3d713cac,0xbd800000,0x3d673cdb,0xbd22bd46,0x3c793d78,0x3c48bd7b,0xbd183d4e,0x3d62bcf1,0xbd803b49,
0x3cc43d6d,0x3b49bd80,0xbcf13d62,0x3d4ebd18,0xbd7b3c48,0x3d783c79,0xbd46bd22,0x3cdb3d67,0xbd35bd35,0x3cac3d71,0x3bc9bd7f,0xbd043d5c,0x3d55bd0e,0xbd7d3c16,0x3d753c95,0xbd3ebd2c,
0xbc48bd7b,0xbcdb3d67,0x3d62bcf1,0xbd7dbc16,0xbcc43d6d,0x3d5cbd04,0xbd7fbbc9,0x3d3e3d2c,0x3d55bd0e,0xbd80bb49,0x3d463d22,0xbc79bd78,0xbd800000,0x3d4e3d18,0xbc95bd75,0xbcac3d71,
0xbd0e3d55,0x3d71bcac,0xbd75bc95,0x3d183d4e,0x3d6dbcc4,0xbd78bc79,0x3d223d46,0xbb49bd80,0xbd7bbc48,0x3d2c3d3e,0xbbc9bd7f,0xbd043d5c,0x3d353d35,0xbc16bd7d,0xbcf13d62,0x3d67bcdb,
0xbd35bd35,0xbb493d80,0x3d46bd22,0xbd7dbc16,0x3d0e3d55,0x3c79bd78,0xbd623cf1,0x3d713cac,0xbcc4bd6d,0xbcdb3d67,0x3d75bc95,0xbd5cbd04,0x3c483d7b,0x3d18bd4e,0xbd7f3bc9,0x3d3e3d2c,
0xbd800000,0x3d2c3d3e,0x3bc9bd7f,0xbd4e3d18,0x3d7b3c48,0xbd04bd5c,0xbc953d75,0x3d67bcdb,0xbd6dbcc4,0x3cac3d71,0x3cf1bd62,0xbd783c79,0x3d553d0e,0xbc16bd7d,0xbd223d46,0x3d80bb49,
0x3c48bd7b,0xbd713cac,0x3d463d22,0x3c16bd7d,0x3d353d35,0x3c79bd78,0xbd753c95,0x3d3e3d2c,0x3d553d0e,0x3b49bd80,0xbd623cf1,0x3d5c3d04,0xbd6d3cc4,0x3d4e3d18,0x3bc9bd7f,0xbd673cdb,
0x3d0e3d55,0x3cdbbd67,0xbd7f3bc9,0x3d183d4e,0xbd800000,0x3d043d5c,0x3cf1bd62,0xbd803b49,0xbd7b3c48,0x3d2c3d3e,0x3c95bd75,0xbd783c79,0x3cc4bd6d,0xbd7d3c16,0x3d223d46,0x3cacbd71,
0x3cc43d6d,0x3d3ebd2c,0xbd62bcf1,0xbc163d7d,0x3d7bbc48,0xbd04bd5c,0xbd223d46,0x3d713cac,0xbd35bd35,0xbcdb3d67,0x3d7f3bc9,0xbc79bd78,0xbd553d0e,0x3d4e3d18,0x3c95bd75,0xbd803b49,
0x3d6d3cc4,0x3b49bd80,0xbd753c95,0x3d183d4e,0x3d0ebd55,0xbd78bc79,0x3bc93d7f,0x3d67bcdb,0xbd800000,0x3cac3d71,0x3d46bd22,0xbd5cbd04,0xbc483d7b,0x3d7dbc16,0xbcf1bd62,0xbd2c3d3e,
0x3d0ebd55,0xbd67bcdb,0xbc953d75,0x3d7d3c16,0x3d6dbcc4,0xbd04bd5c,0xbd463d22,0x3d3e3d2c,0x3d7b3c48,0x3b49bd80,0xbd7f3bc9,0x3c793d78,0x3d353d35,0x3d18bd4e,0xbd62bcf1,0xbcac3d71,
0x3c483d7b,0x3d71bcac,0xbcf1bd62,0xbd4e3d18,0xbcc43d6d,0x3d783c79,0x3bc9bd7f,0xbd803b49,0xbd553d0e,0x3d2c3d3e,0x3d22bd46,0xbd5cbd04,0xbd800000,0x3c163d7d,0x3d75bc95,0xbcdbbd67,
0x3d80,0x3d803b49,0x3bc9bd7f,0xbd7dbc16,0xbc483d7b,0x3d783c79,0x3c95bd75,0xbd71bcac,0xbcc43d6d,0x3d673cdb,0x3cf1bd62,0xbd5cbd04,0xbd0e3d55,0x3d4e3d18,0x3d22bd46,0xbd3ebd2c,
0xbd353d35,0x3d2c3d3e,0x3d46bd22,0xbd18bd4e,0xbd553d0e,0x3d043d5c,0x3d62bcf1,0xbcdbbd67,0xbd6d3cc4,0x3cac3d71,0x3d75bc95,0xbc79bd78,0xbd7b3c48,0x3c163d7d,0x3d7fbbc9,0xbb49bd80,
0xbd553d0e,0x3cac3d71,0x3d7fbbc9,0x3c16bd7d,0x3d80,0x3d783c79,0x3cf1bd62,0xbd3ebd2c,0xbc48bd7b,0xbd80bb49,0xbc953d75,0x3d5c3d04,0xbd6dbcc4,0xbd183d4e,0x3d223d46,0x3d67bcdb,
0x3d7b3c48,0x3cdbbd67,0xbd46bd22,0xbd4e3d18,0x3d35bd35,0xbd04bd5c,0xbd753c95,0x3b493d80,0xbd0e3d55,0x3d2c3d3e,0x3d62bcf1,0xbc79bd78,0x3cc43d6d,0x3d7dbc16,0x3bc9bd7f,0xbd71bcac,
0x3cc4bd6d,0xbd2cbd3e,0xbd753c95,0xbc163d7d,0x3d553d0e,0x3d5cbd04,0xbbc9bd7f,0xbd71bcac,0x3d80,0x3d673cdb,0x3d46bd22,0xbc79bd78,0xbd7bbc48,0xbd183d4e,0x3cf13d62,0x3d80bb49,
0x3d6dbcc4,0x3b49bd80,0xbd62bcf1,0xbd4e3d18,0x3c483d7b,0x3d783c79,0x3d22bd46,0xbcdbbd67,0xbd353d35,0x3cac3d71,0x3d7f3bc9,0x3d04bd5c,0xbd0ebd55,0xbd7d3c16,0xbc953d75,0x3d3e3d2c,
0xbd7b3c48,0xbcdb3d67,0x3cf13d62,0x3d7d3c16,0x3d6d3cc4,0x3d5cbd04,0x3bc9bd7f,0xbd3ebd2c,0xbd0ebd55,0xbd80bb49,0xbd223d46,0x3c793d78,0x3d80,0x3d4e3d18,0x3d75bc95,0x3cacbd71,
0x3d553d0e,0x3d71bcac,0x3c95bd75,0xbd18bd4e,0xbcc4bd6d,0xbd78bc79,0xbd463d22,0x3b493d80,0xbc483d7b,0x3d2c3d3e,0x3d7fbbc9,0x3d04bd5c,0x3d35bd35,0xbc16bd7d,0xbd62bcf1,0xbd673cdb,
0xbd353d35,0xbb493d80,0x3d223d46,0x3d7d3c16,0x3d55bd0e,0x3c79bd78,0xbcf1bd62,0xbd71bcac,0xbd6d3cc4,0xbcdb3d67,0x3c953d75,0x3d5c3d04,0x3d7bbc48,0x3d18bd4e,0xbbc9bd7f,0xbd3ebd2c,
0x3d80,0x3d2c3d3e,0x3d7f3bc9,0x3d4ebd18,0x3c48bd7b,0xbd04bd5c,0xbd75bc95,0xbd673cdb,0xbcc43d6d,0x3cac3d71,0x3d623cf1,0x3d78bc79,0x3d0ebd55,0xbc16bd7d,0xbd46bd22,0xbd803b49,
0xbd7bbc48,0xbd713cac,0xbd223d46,0xbc163d7d,0x3d35bd35,0x3c79bd78,0xbc95bd75,0xbd3ebd2c,0x3d0ebd55,0x3b49bd80,0xbcf1bd62,0xbd5cbd04,0x3cc43d6d,0x3d4e3d18,0x3d7f3bc9,0x3d67bcdb,
0x3d55bd0e,0x3cdbbd67,0xbbc9bd7f,0xbd18bd4e,0x3d80,0x3d043d5c,0x3d623cf1,0x3d80bb49,0x3c483d7b,0x3d2c3d3e,0x3d753c95,0x3d78bc79,0xbd6dbcc4,0xbd7d3c16,0xbd463d22,0xbcac3d71,
0x3d6dbcc4,0x3d3ebd2c,0x3cf1bd62,0x3c16bd7d,0xbc48bd7b,0xbd04bd5c,0xbd46bd22,0xbd71bcac,0xbd353d35,0xbcdb3d67,0xbbc93d7f,0x3c793d78,0x3d0e3d55,0x3d4e3d18,0x3d753c95,0x3d80bb49,
0x3cc4bd6d,0x3b49bd80,0xbc95bd75,0xbd18bd4e,0xbd55bd0e,0xbd78bc79,0xbd7f3bc9,0xbd673cdb,0x3d80,0x3cac3d71,0x3d223d46,0x3d5c3d04,0x3d7b3c48,0x3d7dbc16,0x3d62bcf1,0x3d2cbd3e,
0xbd55bd0e,0xbd67bcdb,0xbd75bc95,0xbd7dbc16,0xbcc4bd6d,0xbd04bd5c,0xbd22bd46,0xbd3ebd2c,0x3c48bd7b,0x3b49bd80,0xbbc9bd7f,0xbc79bd78,0x3d35bd35,0x3d18bd4e,0x3cf1bd62,0x3cacbd71,
0x3d7bbc48,0x3d71bcac,0x3d62bcf1,0x3d4ebd18,0x3d6d3cc4,0x3d783c79,0x3d7f3bc9,0x3d80bb49,0x3d0e3d55,0x3d2c3d3e,0x3d463d22,0x3d5c3d04,0x3d80,0x3c163d7d,0x3c953d75,0x3cdb3d67,
0xbd800000,0xbb493d80,0x3d7f3bc9,0x3c16bd7d,0xbd7bbc48,0xbc793d78,0x3d753c95,0x3cacbd71,0xbd6dbcc4,0xbcdb3d67,0x3d623cf1,0x3d04bd5c,0xbd55bd0e,0xbd183d4e,0x3d463d22,0x3d2cbd3e,
0xbd35bd35,0xbd3e3d2c,0x3d223d46,0x3d4ebd18,0xbd0ebd55,0xbd5c3d04,0x3cf13d62,0x3d67bcdb,0xbcc4bd6d,0xbd713cac,0x3c953d75,0x3d78bc79,0xbc48bd7b,0xbd7d3c16,0x3bc93d7f,0x3d80bb49,
0xbd0ebd55,0xbd713cac,0x3bc93d7f,0x3d7d3c16,0xbd800000,0xbc793d78,0x3d623cf1,0x3d2cbd3e,0x3d7bbc48,0x3b49bd80,0xbd75bc95,0xbd043d5c,0x3cc4bd6d,0xbd4ebd18,0xbd463d22,0x3cdb3d67,
0xbc483d7b,0x3d673cdb,0x3d22bd46,0xbd18bd4e,0x3d353d35,0x3d5cbd04,0xbc95bd75,0xbd803b49,0xbd55bd0e,0xbd3e3d2c,0x3cf13d62,0x3d78bc79,0xbd6d3cc4,0x3c163d7d,0x3d7f3bc9,0x3cacbd71,
0x3d6d3cc4,0x3d3ebd2c,0xbc95bd75,0xbd7dbc16,0xbd0e3d55,0x3d043d5c,0x3d7fbbc9,0x3cacbd71,0xbd800000,0xbcdb3d67,0x3d223d46,0x3d78bc79,0x3c48bd7b,0xbd4ebd18,0xbd623cf1,0x3b493d80,
0x3cc43d6d,0x3d803b49,0x3cf1bd62,0xbd18bd4e,0xbd7b3c48,0xbc793d78,0x3d463d22,0x3d67bcdb,0xbd35bd35,0xbd713cac,0xbbc93d7f,0x3d5c3d04,0x3d55bd0e,0xbc16bd7d,0xbd75bc95,0xbd2c3d3e,
0xbc48bd7b,0xbd67bcdb,0xbd623cf1,0xbc163d7d,0xbcc43d6d,0x3d043d5c,0x3d7f3bc9,0x3d2cbd3e,0x3d55bd0e,0x3b49bd80,0xbd46bd22,0xbd783c79,0xbd800000,0xbd183d4e,0x3c953d75,0x3d713cac,
0xbd0e3d55,0x3cac3d71,0x3d753c95,0x3d4ebd18,0x3d6dbcc4,0x3c79bd78,0xbd22bd46,0xbd803b49,0xbd7bbc48,0xbd3e3d2c,0x3bc93d7f,0x3d5c3d04,0x3d353d35,0x3d7dbc16,0x3cf1bd62,0xbcdbbd67,
0xbd35bd35,0xbd80bb49,0xbd463d22,0xbc163d7d,0x3d0e3d55,0x3d783c79,0x3d62bcf1,0x3cacbd71,0xbcc4bd6d,0xbd67bcdb,0xbd753c95,0xbd043d5c,0x3c483d7b,0x3d4e3d18,0x3d7fbbc9,0x3d2cbd3e,
0xbd800000,0xbd3e3d2c,0xbbc93d7f,0x3d183d4e,0x3d7b3c48,0x3d5cbd04,0x3c95bd75,0xbcdbbd67,0xbd6dbcc4,0xbd713cac,0xbcf13d62,0x3c793d78,0x3d553d0e,0x3d7dbc16,0x3d22bd46,0xbb49bd80,
0x3c48bd7b,0xbcacbd71,0xbd46bd22,0xbd7dbc16,0x3d353d35,0x3d783c79,0x3d75bc95,0x3d2cbd3e,0x3d553d0e,0x3d803b49,0x3d62bcf1,0x3d04bd5c,0xbd6d3cc4,0xbd183d4e,0xbbc93d7f,0x3cdb3d67,
0x3d0e3d55,0x3d673cdb,0x3d7fbbc9,0x3d4ebd18,0xbd800000,0xbd5c3d04,0xbcf13d62,0x3b493d80,0xbd7b3c48,0xbd3e3d2c,0xbc953d75,0x3c793d78,0x3cc4bd6d,0xbc16bd7d,0xbd22bd46,0xbd71bcac,
0x3cc43d6d,0x3d2c3d3e,0x3d623cf1,0x3d7d3c16,0x3d7bbc48,0x3d5cbd04,0x3d22bd46,0x3cacbd71,0xbd35bd35,0xbd67bcdb,0xbd7fbbc9,0xbd783c79,0xbd553d0e,0xbd183d4e,0xbc953d75,0x3b493d80,
0x3d6d3cc4,0x3d803b49,0x3d75bc95,0x3d4ebd18,0x3d0ebd55,0x3c79bd78,0xbbc9bd7f,0xbcdbbd67,0xbd800000,0xbd713cac,0xbd463d22,0xbd043d5c,0xbc483d7b,0x3c163d7d,0x3cf13d62,0x3d3e3d2c,
0x3d0ebd55,0x3cdbbd67,0x3c95bd75,0x3c16bd7d,0x3d6dbcc4,0x3d5cbd04,0x3d46bd22,0x3d2cbd3e,0x3d7b3c48,0x3d803b49,0x3d7fbbc9,0x3d78bc79,0x3d353d35,0x3d4e3d18,0x3d623cf1,0x3d713cac,
0x3c483d7b,0x3cac3d71,0x3cf13d62,0x3d183d4e,0xbcc43d6d,0xbc793d78,0xbbc93d7f,0x3b493d80,0xbd553d0e,0xbd3e3d2c,0xbd223d46,0xbd043d5c,0xbd800000,0xbd7d3c16,0xbd753c95,0xbd673cdb,
0x3d80,0xbbc93d7f,0xbc483d7b,0xbc953d75,0xbcc43d6d,0xbcf13d62,0xbd0e3d55,0xbd223d46,0xbd353d35,0xbd463d22,0xbd553d0e,0xbd623cf1,0xbd6d3cc4,0xbd753c95,0xbd7b3c48,0xbd7f3bc9,
0xbd800000,0xbd7fbbc9,0xbd7bbc48,0xbd75bc95,0xbd6dbcc4,0xbd62bcf1,0xbd55bd0e,0xbd46bd22,0xbd35bd35,0xbd22bd46,0xbd0ebd55,0xbcf1bd62,0xbcc4bd6d,0xbc95bd75,0xbc48bd7b,0xbbc9bd7f,
0xbd6d3cc4,0xbd7f3bc9,0xbd7bbc48,0xbd62bcf1,0x3d80,0xbc953d75,0xbd0e3d55,0xbd463d22,0x3cc4bd6d,0x3d22bd46,0x3d55bd0e,0x3d75bc95,0xbd35bd35,0xbcf1bd62,0xbc48bd7b,0x3bc9bd7f,
0x3cc43d6d,0x3bc93d7f,0xbc483d7b,0xbcf13d62,0x3d800000,0x3d753c95,0x3d553d0e,0x3d223d46,0xbd6dbcc4,0xbd46bd22,0xbd0ebd55,0xbc95bd75,0xbd353d35,0xbd623cf1,0xbd7b3c48,0xbd7fbbc9,
0x3d35bd35,0x3d75bc95,0x3d7b3c48,0x3d463d22,0x3cc43d6d,0xbbc93d7f,0xbd0e3d55,0xbd623cf1,0x3d80,0xbcf13d62,0xbd553d0e,0xbd7f3bc9,0xbd6dbcc4,0xbd22bd46,0xbc48bd7b,0x3c95bd75,
0x3d353d35,0x3c953d75,0xbc483d7b,0xbd223d46,0xbd6d3cc4,0xbd7fbbc9,0xbd55bd0e,0xbcf1bd62,0xbd800000,0xbd62bcf1,0xbd0ebd55,0xbbc9bd7f,0x3cc4bd6d,0x3d46bd22,0x3d7bbc48,0x3d753c95,
0xbd6dbcc4,0xbcf1bd62,0x3c48bd7b,0x3d46bd22,0x3d353d35,0x3bc93d7f,0xbd0e3d55,0xbd753c95,0xbcc4bd6d,0x3c95bd75,0x3d55bd0e,0x3d7f3bc9,0x3d80,0xbd223d46,0xbd7b3c48,0xbd62bcf1,
0xbcc43d6d,0xbd623cf1,0xbd7bbc48,0xbd22bd46,0x3d35bd35,0x3d7fbbc9,0x3d553d0e,0x3c953d75,0xbd6d3cc4,0xbd75bc95,0xbd0ebd55,0x3bc9bd7f,0x3d800000,0x3d463d22,0x3c483d7b,0xbcf13d62,
0xbd800000,0xbd22bd46,0x3c48bd7b,0x3d62bcf1,0x3d6d3cc4,0x3c953d75,0xbd0e3d55,0xbd7f3bc9,0xbd35bd35,0x3bc9bd7f,0x3d55bd0e,0x3d753c95,0x3cc43d6d,0xbcf13d62,0xbd7b3c48,0xbd46bd22,
0x3d80,0xbd463d22,0xbd7bbc48,0xbcf1bd62,0x3cc4bd6d,0x3d75bc95,0x3d553d0e,0x3bc93d7f,0xbd353d35,0xbd7fbbc9,0xbd0ebd55,0x3c95bd75,0x3d6dbcc4,0x3d623cf1,0x3c483d7b,0xbd223d46,
0xbcc4bd6d,0x3d22bd46,0x3d7b3c48,0x3c953d75,0x3d800000,0x3cf13d62,0xbd0e3d55,0xbd7fbbc9,0x3d6d3cc4,0x3bc93d7f,0xbd553d0e,0xbd62bcf1,0xbd353d35,0xbd75bc95,0xbc48bd7b,0x3d46bd22,
0x3d6dbcc4,0x3d463d22,0xbc483d7b,0xbd753c95,0x3d80,0xbd623cf1,0xbd55bd0e,0x3bc9bd7f,0xbcc43d6d,0xbd7f3bc9,0xbd0ebd55,0x3cf1bd62,0xbd35bd35,0x3c95bd75,0x3d7bbc48,0x3d223d46,
0x3d353d35,0xbcf13d62,0xbd7bbc48,0xbbc9bd7f,0x3d6dbcc4,0x3d223d46,0xbd0e3d55,0xbd75bc95,0xbd800000,0xbc95bd75,0x3d55bd0e,0x3d463d22,0xbcc43d6d,0xbd7fbbc9,0xbc48bd7b,0x3d62bcf1,
0x3d35bd35,0x3d623cf1,0xbc483d7b,0xbd7f3bc9,0xbcc4bd6d,0x3d46bd22,0x3d553d0e,0xbc953d75,0x3d80,0xbd753c95,0xbd0ebd55,0x3d22bd46,0x3d6d3cc4,0xbbc93d7f,0xbd7b3c48,0xbcf1bd62,
0x3cc4bd6d,0x3d753c95,0xbc483d7b,0xbd7fbbc9,0x3d35bd35,0x3d463d22,0xbd0e3d55,0xbd62bcf1,0x3d6dbcc4,0x3cf13d62,0xbd553d0e,0xbd22bd46,0x3d800000,0x3bc93d7f,0xbd7b3c48,0xbc95bd75,
0x3d6d3cc4,0xbc953d75,0xbd7bbc48,0x3bc9bd7f,0x3d353d35,0xbd223d46,0xbd55bd0e,0x3cf1bd62,0x3cc43d6d,0xbd623cf1,0xbd0ebd55,0x3d46bd22,0x3d80,0xbd7f3bc9,0xbc48bd7b,0x3d75bc95,
0xbd800000,0xbd7fbbc9,0xbd7bbc48,0xbd75bc95,0xbd6dbcc4,0xbd62bcf1,0xbd55bd0e,0xbd46bd22,0xbd35bd35,0xbd22bd46,0xbd0ebd55,0xbcf1bd62,0xbcc4bd6d,0xbc95bd75,0xbc48bd7b,0xbbc9bd7f,
0x8000bd80,0x3bc9bd7f,0x3c48bd7b,0x3c95bd75,0x3cc4bd6d,0x3cf1bd62,0x3d0ebd55,0x3d22bd46,0x3d35bd35,0x3d46bd22,0x3d55bd0e,0x3d62bcf1,0x3d6dbcc4,0x3d75bc95,0x3d7bbc48,0x3d7fbbc9,
0xbcc4bd6d,0xbbc9bd7f,0x3c48bd7b,0x3cf1bd62,0xbd800000,0xbd75bc95,0xbd55bd0e,0xbd22bd46,0x3d6d3cc4,0x3d463d22,0x3d0e3d55,0x3c953d75,0x3d35bd35,0x3d62bcf1,0x3d7bbc48,0x3d7f3bc9,
0xbd6d3cc4,0xbd7f3bc9,0xbd7bbc48,0xbd62bcf1,0x80003d80,0xbc953d75,0xbd0e3d55,0xbd463d22,0x3cc4bd6d,0x3d22bd46,0x3d55bd0e,0x3d75bc95,0xbd35bd35,0xbcf1bd62,0xbc48bd7b,0x3bc9bd7f,
0x3d353d35,0x3c953d75,0xbc483d7b,0xbd223d46,0xbd6d3cc4,0xbd7fbbc9,0xbd55bd0e,0xbcf1bd62,0xbd800000,0xbd62bcf1,0xbd0ebd55,0xbbc9bd7f,0x3cc4bd6d,0x3d46bd22,0x3d7bbc48,0x3d753c95,
0xbd353d35,0xbd753c95,0xbd7bbc48,0xbd46bd22,0xbcc4bd6d,0x3bc9bd7f,0x3d0ebd55,0x3d62bcf1,0x8000bd80,0x3cf1bd62,0x3d55bd0e,0x3d7fbbc9,0x3d6d3cc4,0x3d223d46,0x3c483d7b,0xbc953d75,
0x3cc4bd6d,0x3d62bcf1,0x3d7b3c48,0x3d223d46,0xbd353d35,0xbd7f3bc9,0xbd55bd0e,0xbc95bd75,0x3d6dbcc4,0x3d753c95,0x3d0e3d55,0xbbc93d7f,0xbd800000,0xbd46bd22,0xbc48bd7b,0x3cf1bd62,
0xbd6dbcc4,0xbcf1bd62,0x3c48bd7b,0x3d46bd22,0x3d353d35,0x3bc93d7f,0xbd0e3d55,0xbd753c95,0xbcc4bd6d,0x3c95bd75,0x3d55bd0e,0x3d7f3bc9,0x80003d80,0xbd223d46,0xbd7b3c48,0xbd62bcf1,
0x8000bd80,0x3d46bd22,0x3d7b3c48,0x3cf13d62,0xbcc43d6d,0xbd753c95,0xbd55bd0e,0xbbc9bd7f,0x3d35bd35,0x3d7f3bc9,0x3d0e3d55,0xbc953d75,0xbd6d3cc4,0xbd62bcf1,0xbc48bd7b,0x3d22bd46,
0xbd800000,0xbd22bd46,0x3c48bd7b,0x3d62bcf1,0x3d6d3cc4,0x3c953d75,0xbd0e3d55,0xbd7f3bc9,0xbd35bd35,0x3bc9bd7f,0x3d55bd0e,0x3d753c95,0x3cc43d6d,0xbcf13d62,0xbd7b3c48,0xbd46bd22,
0x3d6dbcc4,0x3d463d22,0xbc483d7b,0xbd753c95,0x80003d80,0xbd623cf1,0xbd55bd0e,0x3bc9bd7f,0xbcc43d6d,0xbd7f3bc9,0xbd0ebd55,0x3cf1bd62,0xbd35bd35,0x3c95bd75,0x3d7bbc48,0x3d223d46,
0x3cc43d6d,0xbd223d46,0xbd7bbc48,0xbc95bd75,0xbd800000,0xbcf1bd62,0x3d0ebd55,0x3d7f3bc9,0xbd6dbcc4,0xbbc9bd7f,0x3d55bd0e,0x3d623cf1,0x3d35bd35,0x3d753c95,0x3c483d7b,0xbd463d22,
0xbd353d35,0xbd62bcf1,0x3c48bd7b,0x3d7fbbc9,0x3cc43d6d,0xbd463d22,0xbd55bd0e,0x3c95bd75,0x8000bd80,0x3d75bc95,0x3d0e3d55,0xbd223d46,0xbd6dbcc4,0x3bc9bd7f,0x3d7bbc48,0x3cf13d62,
0x3d353d35,0xbcf13d62,0xbd7bbc48,0xbbc9bd7f,0x3d6dbcc4,0x3d223d46,0xbd0e3d55,0xbd75bc95,0xbd800000,0xbc95bd75,0x3d55bd0e,0x3d463d22,0xbcc43d6d,0xbd7fbbc9,0xbc48bd7b,0x3d62bcf1,
0x3d6d3cc4,0xbc953d75,0xbd7bbc48,0x3bc9bd7f,0x3d353d35,0xbd223d46,0xbd55bd0e,0x3cf1bd62,0x3cc43d6d,0xbd623cf1,0xbd0ebd55,0x3d46bd22,0x80003d80,0xbd7f3bc9,0xbc48bd7b,0x3d75bc95,
0xbcc43d6d,0xbd75bc95,0x3c48bd7b,0x3d7f3bc9,0xbd353d35,0xbd46bd22,0x3d0ebd55,0x3d623cf1,0xbd6d3cc4,0xbcf1bd62,0x3d55bd0e,0x3d223d46,0xbd800000,0xbbc9bd7f,0x3d7bbc48,0x3c953d75,
0x3d80,0xbd7fbbc9,0x3c48bd7b,0x3d753c95,0xbcc43d6d,0xbd62bcf1,0x3d0ebd55,0x3d463d22,0xbd353d35,0xbd22bd46,0x3d55bd0e,0x3cf13d62,0xbd6d3cc4,0xbc95bd75,0x3d7bbc48,0x3bc93d7f,
0xbd800000,0x3bc9bd7f,0x3d7b3c48,0xbc953d75,0xbd6dbcc4,0x3cf1bd62,0x3d553d0e,0xbd223d46,0xbd35bd35,0x3d46bd22,0x3d0e3d55,0xbd623cf1,0xbcc4bd6d,0x3d75bc95,0x3c483d7b,0xbd7f3bc9,
0xbd6d3cc4,0xbbc9bd7f,0x3d7b3c48,0xbcf13d62,0x3d80,0xbd75bc95,0x3d0ebd55,0x3d223d46,0x3cc4bd6d,0x3d463d22,0xbd553d0e,0xbc95bd75,0xbd35bd35,0x3d62bcf1,0x3c483d7b,0xbd7fbbc9,
0x3cc43d6d,0xbd7f3bc9,0x3c48bd7b,0x3d623cf1,0x3d800000,0xbc953d75,0xbd55bd0e,0x3d46bd22,0xbd6dbcc4,0x3d22bd46,0x3d0e3d55,0xbd753c95,0xbd353d35,0xbcf1bd62,0x3d7bbc48,0xbbc93d7f,
0x3d35bd35,0x3c953d75,0xbd7bbc48,0x3d22bd46,0x3cc43d6d,0xbd7fbbc9,0x3d0ebd55,0x3cf13d62,0x3d80,0xbd62bcf1,0x3d55bd0e,0x3bc93d7f,0xbd6dbcc4,0x3d46bd22,0x3c483d7b,0xbd75bc95,
0x3d353d35,0xbd753c95,0x3c48bd7b,0x3d463d22,0xbd6d3cc4,0x3bc9bd7f,0x3d553d0e,0xbd623cf1,0xbd800000,0x3cf1bd62,0x3d0e3d55,0xbd7f3bc9,0x3cc4bd6d,0x3d223d46,0xbd7b3c48,0x3c95bd75,
0xbd6dbcc4,0x3d62bcf1,0xbc483d7b,0xbd22bd46,0x3d353d35,0xbd7f3bc9,0x3d0ebd55,0x3c953d75,0xbcc4bd6d,0x3d753c95,0xbd553d0e,0x3bc9bd7f,0x3d80,0xbd46bd22,0x3d7bbc48,0xbcf13d62,
0xbcc43d6d,0xbcf1bd62,0x3d7b3c48,0xbd463d22,0x3d35bd35,0x3bc93d7f,0xbd55bd0e,0x3d75bc95,0xbd6d3cc4,0x3c95bd75,0x3d0e3d55,0xbd7fbbc9,0x3d800000,0xbd223d46,0xbc48bd7b,0x3d623cf1,
0xbd800000,0x3d46bd22,0xbc483d7b,0xbcf1bd62,0x3d6d3cc4,0xbd753c95,0x3d0ebd55,0x3bc93d7f,0xbd35bd35,0x3d7f3bc9,0xbd553d0e,0x3c95bd75,0x3cc43d6d,0xbd62bcf1,0x3d7bbc48,0xbd223d46,
0x3d80,0xbd22bd46,0x3d7b3c48,0xbd623cf1,0x3cc4bd6d,0x3c953d75,0xbd55bd0e,0x3d7fbbc9,0xbd353d35,0x3bc9bd7f,0x3d0e3d55,0xbd75bc95,0x3d6dbcc4,0xbcf13d62,0xbc48bd7b,0x3d463d22,
0xbcc4bd6d,0x3d463d22,0xbd7bbc48,0x3d75bc95,0x3d800000,0xbd623cf1,0x3d0ebd55,0xbbc93d7f,0x3d6d3cc4,0xbd7f3bc9,0x3d55bd0e,0xbcf13d62,0xbd353d35,0x3c95bd75,0x3c483d7b,0xbd22bd46,
0x3d6dbcc4,0xbd223d46,0x3c48bd7b,0x3c953d75,0x3d80,0xbcf1bd62,0x3d553d0e,0xbd7fbbc9,0xbcc43d6d,0xbbc9bd7f,0x3d0e3d55,0xbd62bcf1,0xbd35bd35,0x3d753c95,0xbd7b3c48,0x3d46bd22,
0x3d353d35,0xbd62bcf1,0x3d7b3c48,0xbd7f3bc9,0x3d6dbcc4,0xbd463d22,0x3d0ebd55,0xbc953d75,0xbd800000,0x3d75bc95,0xbd553d0e,0x3d22bd46,0xbcc43d6d,0x3bc9bd7f,0x3c483d7b,0xbcf1bd62,
0x3d35bd35,0xbcf13d62,0x3c48bd7b,0x3bc93d7f,0xbcc4bd6d,0x3d223d46,0xbd55bd0e,0x3d753c95,0x3d80,0xbc95bd75,0x3d0e3d55,0xbd46bd22,0x3d6d3cc4,0xbd7fbbc9,0x3d7bbc48,0xbd623cf1,
0x3cc4bd6d,0xbc953d75,0x3c48bd7b,0xbbc93d7f,0x3d35bd35,0xbd223d46,0x3d0ebd55,0xbcf13d62,0x3d6dbcc4,0xbd623cf1,0x3d55bd0e,0xbd463d22,0x3d800000,0xbd7f3bc9,0x3d7bbc48,0xbd753c95,
0x3d6d3cc4,0xbd75bc95,0x3d7b3c48,0xbd7fbbc9,0x3d353d35,0xbd46bd22,0x3d553d0e,0xbd62bcf1,0x3cc43d6d,0xbcf1bd62,0x3d0e3d55,0xbd22bd46,0x3d80,0xbbc9bd7f,0x3c483d7b,0xbc95bd75,
0xbd800000,0x3bc9bd7f,0x3d7b3c48,0xbc953d75,0xbd6dbcc4,0x3cf1bd62,0x3d553d0e,0xbd223d46,0xbd35bd35,0x3d46bd22,0x3d0e3d55,0xbd623cf1,0xbcc4bd6d,0x3d75bc95,0x3c483d7b,0xbd7f3bc9,
0x8000bd80,0x3d7f3bc9,0xbc483d7b,0xbd75bc95,0x3cc4bd6d,0x3d623cf1,0xbd0e3d55,0xbd46bd22,0x3d35bd35,0x3d223d46,0xbd553d0e,0xbcf1bd62,0x3d6dbcc4,0x3c953d75,0xbd7b3c48,0xbbc9bd7f,
0xbcc4bd6d,0x3d7fbbc9,0xbc483d7b,0xbd62bcf1,0xbd800000,0x3c95bd75,0x3d553d0e,0xbd463d22,0x3d6d3cc4,0xbd223d46,0xbd0ebd55,0x3d75bc95,0x3d35bd35,0x3cf13d62,0xbd7b3c48,0x3bc9bd7f,
0xbd6d3cc4,0xbbc9bd7f,0x3d7b3c48,0xbcf13d62,0x80003d80,0xbd75bc95,0x3d0ebd55,0x3d223d46,0x3cc4bd6d,0x3d463d22,0xbd553d0e,0xbc95bd75,0xbd35bd35,0x3d62bcf1,0x3c483d7b,0xbd7fbbc9,
0x3d353d35,0xbd753c95,0x3c48bd7b,0x3d463d22,0xbd6d3cc4,0x3bc9bd7f,0x3d553d0e,0xbd623cf1,0xbd800000,0x3cf1bd62,0x3d0e3d55,0xbd7f3bc9,0x3cc4bd6d,0x3d223d46,0xbd7b3c48,0x3c95bd75,
0xbd353d35,0xbc95bd75,0x3d7b3c48,0xbd223d46,0xbcc4bd6d,0x3d7f3bc9,0xbd0e3d55,0xbcf1bd62,0x8000bd80,0x3d623cf1,0xbd553d0e,0xbbc9bd7f,0x3d6d3cc4,0xbd463d22,0xbc48bd7b,0x3d753c95,
0x3cc4bd6d,0x3cf13d62,0xbd7bbc48,0x3d46bd22,0xbd353d35,0xbbc9bd7f,0x3d553d0e,0xbd753c95,0x3d6dbcc4,0xbc953d75,0xbd0ebd55,0x3d7f3bc9,0xbd800000,0x3d22bd46,0x3c483d7b,0xbd62bcf1,
0xbd6dbcc4,0x3d62bcf1,0xbc483d7b,0xbd22bd46,0x3d353d35,0xbd7f3bc9,0x3d0ebd55,0x3c953d75,0xbcc4bd6d,0x3d753c95,0xbd553d0e,0x3bc9bd7f,0x80003d80,0xbd46bd22,0x3d7bbc48,0xbcf13d62,
0x8000bd80,0x3d223d46,0xbd7bbc48,0x3d62bcf1,0xbcc43d6d,0xbc95bd75,0x3d553d0e,0xbd7f3bc9,0x3d35bd35,0xbbc93d7f,0xbd0ebd55,0x3d753c95,0xbd6d3cc4,0x3cf1bd62,0x3c483d7b,0xbd46bd22,
0xbd800000,0x3d46bd22,0xbc483d7b,0xbcf1bd62,0x3d6d3cc4,0xbd753c95,0x3d0ebd55,0x3bc93d7f,0xbd35bd35,0x3d7f3bc9,0xbd553d0e,0x3c95bd75,0x3cc43d6d,0xbd62bcf1,0x3d7bbc48,0xbd223d46,
0x3d6dbcc4,0xbd223d46,0x3c48bd7b,0x3c953d75,0x80003d80,0xbcf1bd62,0x3d553d0e,0xbd7fbbc9,0xbcc43d6d,0xbbc9bd7f,0x3d0e3d55,0xbd62bcf1,0xbd35bd35,0x3d753c95,0xbd7b3c48,0x3d46bd22,
0x3cc43d6d,0xbd46bd22,0x3d7b3c48,0xbd753c95,0xbd800000,0x3d62bcf1,0xbd0e3d55,0x3bc9bd7f,0xbd6dbcc4,0x3d7fbbc9,0xbd553d0e,0x3cf1bd62,0x3d35bd35,0xbc953d75,0xbc48bd7b,0x3d223d46,
0xbd353d35,0x3cf1bd62,0xbc483d7b,0xbbc9bd7f,0x3cc43d6d,0xbd22bd46,0x3d553d0e,0xbd75bc95,0x8000bd80,0x3c953d75,0xbd0ebd55,0x3d463d22,0xbd6dbcc4,0x3d7f3bc9,0xbd7b3c48,0x3d62bcf1,
0x3d353d35,0xbd62bcf1,0x3d7b3c48,0xbd7f3bc9,0x3d6dbcc4,0xbd463d22,0x3d0ebd55,0xbc953d75,0xbd800000,0x3d75bc95,0xbd553d0e,0x3d22bd46,0xbcc43d6d,0x3bc9bd7f,0x3c483d7b,0xbcf1bd62,
0x3d6d3cc4,0xbd75bc95,0x3d7b3c48,0xbd7fbbc9,0x3d353d35,0xbd46bd22,0x3d553d0e,0xbd62bcf1,0x3cc43d6d,0xbcf1bd62,0x3d0e3d55,0xbd22bd46,0x80003d80,0xbbc9bd7f,0x3c483d7b,0xbc95bd75,
0xbcc43d6d,0x3c95bd75,0xbc483d7b,0x3bc9bd7f,0xbd353d35,0x3d22bd46,0xbd0e3d55,0x3cf1bd62,0xbd6d3cc4,0x3d62bcf1,0xbd553d0e,0x3d46bd22,0xbd800000,0x3d7fbbc9,0xbd7b3c48,0x3d75bc95,
0x3d80,0x3bc9bd7f,0xbc483d7b,0x3c95bd75,0xbcc43d6d,0x3cf1bd62,0xbd0e3d55,0x3d22bd46,0xbd353d35,0x3d46bd22,0xbd553d0e,0x3d62bcf1,0xbd6d3cc4,0x3d75bc95,0xbd7b3c48,0x3d7fbbc9,
0xbd800000,0x3d7f3bc9,0xbd7bbc48,0x3d753c95,0xbd6dbcc4,0x3d623cf1,0xbd55bd0e,0x3d463d22,0xbd35bd35,0x3d223d46,0xbd0ebd55,0x3cf13d62,0xbcc4bd6d,0x3c953d75,0xbc48bd7b,0x3bc93d7f,
0xbd6d3cc4,0x3d7fbbc9,0xbd7bbc48,0x3d623cf1,0x3d80,0x3c95bd75,0xbd0e3d55,0x3d46bd22,0x3cc4bd6d,0xbd223d46,0x3d55bd0e,0xbd753c95,0xbd35bd35,0x3cf13d62,0xbc48bd7b,0xbbc93d7f,
0x3cc43d6d,0xbbc9bd7f,0xbc483d7b,0x3cf1bd62,0x3d800000,0xbd75bc95,0x3d553d0e,0xbd22bd46,0xbd6dbcc4,0x3d463d22,0xbd0ebd55,0x3c953d75,0xbd353d35,0x3d62bcf1,0xbd7b3c48,0x3d7f3bc9,
0x3d35bd35,0xbd753c95,0x3d7b3c48,0xbd46bd22,0x3cc43d6d,0x3bc9bd7f,0xbd0e3d55,0x3d62bcf1,0x3d80,0x3cf1bd62,0xbd553d0e,0x3d7fbbc9,0xbd6dbcc4,0x3d223d46,0xbc48bd7b,0xbc953d75,
0x3d353d35,0xbc95bd75,0xbc483d7b,0x3d22bd46,0xbd6d3cc4,0x3d7f3bc9,0xbd55bd0e,0x3cf13d62,0xbd800000,0x3d623cf1,0xbd0ebd55,0x3bc93d7f,0x3cc4bd6d,0xbd463d22,0x3d7bbc48,0xbd75bc95,
0xbd6dbcc4,0x3cf13d62,0x3c48bd7b,0xbd463d22,0x3d353d35,0xbbc9bd7f,0xbd0e3d55,0x3d75bc95,0xbcc4bd6d,0xbc953d75,0x3d55bd0e,0xbd7fbbc9,0x3d80,0x3d22bd46,0xbd7b3c48,0x3d623cf1,
0xbcc43d6d,0x3d62bcf1,0xbd7bbc48,0x3d223d46,0x3d35bd35,0xbd7f3bc9,0x3d553d0e,0xbc95bd75,0xbd6d3cc4,0x3d753c95,0xbd0ebd55,0xbbc93d7f,0x3d800000,0xbd46bd22,0x3c483d7b,0x3cf1bd62,
0xbd800000,0x3d223d46,0x3c48bd7b,0xbd623cf1,0x3d6d3cc4,0xbc95bd75,0xbd0e3d55,0x3d7fbbc9,0xbd35bd35,0xbbc93d7f,0x3d55bd0e,0xbd75bc95,0x3cc43d6d,0x3cf1bd62,0xbd7b3c48,0x3d463d22,
0x3d80,0x3d46bd22,0xbd7bbc48,0x3cf13d62,0x3cc4bd6d,0xbd753c95,0x3d553d0e,0xbbc9bd7f,0xbd353d35,0x3d7f3bc9,0xbd0ebd55,0xbc953d75,0x3d6dbcc4,0xbd62bcf1,0x3c483d7b,0x3d22bd46,
0xbcc4bd6d,0xbd223d46,0x3d7b3c48,0xbc95bd75,0x3d800000,0xbcf1bd62,0xbd0e3d55,0x3d7f3bc9,0x3d6d3cc4,0xbbc9bd7f,0xbd553d0e,0x3d623cf1,0xbd353d35,0x3d753c95,0xbc48bd7b,0xbd463d22,
0x3d6dbcc4,0xbd46bd22,0xbc483d7b,0x3d75bc95,0x3d80,0x3d62bcf1,0xbd55bd0e,0xbbc93d7f,0xbcc43d6d,0x3d7fbbc9,0xbd0ebd55,0xbcf13d62,0xbd35bd35,0xbc953d75,0x3d7bbc48,0xbd22bd46,
0x3d353d35,0x3cf1bd62,0xbd7bbc48,0x3bc93d7f,0x3d6dbcc4,0xbd22bd46,0xbd0e3d55,0x3d753c95,0xbd800000,0x3c953d75,0x3d55bd0e,0xbd46bd22,0xbcc43d6d,0x3d7f3bc9,0xbc48bd7b,0xbd623cf1,
0x3d35bd35,0xbd62bcf1,0xbc483d7b,0x3d7fbbc9,0xbcc4bd6d,0xbd463d22,0x3d553d0e,0x3c95bd75,0x3d80,0x3d75bc95,0xbd0ebd55,0xbd223d46,0x3d6d3cc4,0x3bc9bd7f,0xbd7b3c48,0x3cf13d62,
0x3cc4bd6d,0xbd75bc95,0xbc483d7b,0x3d7f3bc9,0x3d35bd35,0xbd46bd22,0xbd0e3d55,0x3d623cf1,0x3d6dbcc4,0xbcf1bd62,0xbd553d0e,0x3d223d46,0x3d800000,0xbbc9bd7f,0xbd7b3c48,0x3c953d75,
0x3d6d3cc4,0x3c95bd75,0xbd7bbc48,0xbbc93d7f,0x3d353d35,0x3d22bd46,0xbd55bd0e,0xbcf13d62,0x3cc43d6d,0x3d62bcf1,0xbd0ebd55,0xbd463d22,0x3d80,0x3d7fbbc9,0xbc48bd7b,0xbd753c95,
0xbd800000,0x3d7f3bc9,0xbd7bbc48,0x3d753c95,0xbd6dbcc4,0x3d623cf1,0xbd55bd0e,0x3d463d22,0xbd35bd35,0x3d223d46,0xbd0ebd55,0x3cf13d62,0xbcc4bd6d,0x3c953d75,0xbc48bd7b,0x3bc93d7f,
0x8000bd80,0xbbc93d7f,0x3c48bd7b,0xbc953d75,0x3cc4bd6d,0xbcf13d62,0x3d0ebd55,0xbd223d46,0x3d35bd35,0xbd463d22,0x3d55bd0e,0xbd623cf1,0x3d6dbcc4,0xbd753c95,0x3d7bbc48,0xbd7f3bc9,
0xbcc4bd6d,0x3bc93d7f,0x3c48bd7b,0xbcf13d62,0xbd800000,0x3d753c95,0xbd55bd0e,0x3d223d46,0x3d6d3cc4,0xbd46bd22,0x3d0e3d55,0xbc95bd75,0x3d35bd35,0xbd623cf1,0x3d7bbc48,0xbd7fbbc9,
0xbd6d3cc4,0x3d7fbbc9,0xbd7bbc48,0x3d623cf1,0x80003d80,0x3c95bd75,0xbd0e3d55,0x3d46bd22,0x3cc4bd6d,0xbd223d46,0x3d55bd0e,0xbd753c95,0xbd35bd35,0x3cf13d62,0xbc48bd7b,0xbbc93d7f,
0x3d353d35,0xbc95bd75,0xbc483d7b,0x3d22bd46,0xbd6d3cc4,0x3d7f3bc9,0xbd55bd0e,0x3cf13d62,0xbd800000,0x3d623cf1,0xbd0ebd55,0x3bc93d7f,0x3cc4bd6d,0xbd463d22,0x3d7bbc48,0xbd75bc95,
0xbd353d35,0x3d75bc95,0xbd7bbc48,0x3d463d22,0xbcc4bd6d,0xbbc93d7f,0x3d0ebd55,0xbd623cf1,0x8000bd80,0xbcf13d62,0x3d55bd0e,0xbd7f3bc9,0x3d6d3cc4,0xbd22bd46,0x3c483d7b,0x3c95bd75,
0x3cc4bd6d,0xbd623cf1,0x3d7b3c48,0xbd22bd46,0xbd353d35,0x3d7fbbc9,0xbd55bd0e,0x3c953d75,0x3d6dbcc4,0xbd75bc95,0x3d0e3d55,0x3bc9bd7f,0xbd800000,0x3d463d22,0xbc48bd7b,0xbcf13d62,
0xbd6dbcc4,0x3cf13d62,0x3c48bd7b,0xbd463d22,0x3d353d35,0xbbc9bd7f,0xbd0e3d55,0x3d75bc95,0xbcc4bd6d,0xbc953d75,0x3d55bd0e,0xbd7fbbc9,0x80003d80,0x3d22bd46,0xbd7b3c48,0x3d623cf1,
0x8000bd80,0xbd463d22,0x3d7b3c48,0xbcf1bd62,0xbcc43d6d,0x3d75bc95,0xbd55bd0e,0x3bc93d7f,0x3d35bd35,0xbd7fbbc9,0x3d0e3d55,0x3c95bd75,0xbd6d3cc4,0x3d623cf1,0xbc48bd7b,0xbd223d46,
0xbd800000,0x3d223d46,0x3c48bd7b,0xbd623cf1,0x3d6d3cc4,0xbc95bd75,0xbd0e3d55,0x3d7fbbc9,0xbd35bd35,0xbbc93d7f,0x3d55bd0e,0xbd75bc95,0x3cc43d6d,0x3cf1bd62,0xbd7b3c48,0x3d463d22,
0x3d6dbcc4,0xbd46bd22,0xbc483d7b,0x3d75bc95,0x80003d80,0x3d62bcf1,0xbd55bd0e,0xbbc93d7f,0xbcc43d6d,0x3d7fbbc9,0xbd0ebd55,0xbcf13d62,0xbd35bd35,0xbc953d75,0x3d7bbc48,0xbd22bd46,
0x3cc43d6d,0x3d22bd46,0xbd7bbc48,0x3c953d75,0xbd800000,0x3cf13d62,0x3d0ebd55,0xbd7fbbc9,0xbd6dbcc4,0x3bc93d7f,0x3d55bd0e,0xbd62bcf1,0x3d35bd35,0xbd75bc95,0x3c483d7b,0x3d46bd22,
0xbd353d35,0x3d623cf1,0x3c48bd7b,0xbd7f3bc9,0x3cc43d6d,0x3d46bd22,0xbd55bd0e,0xbc953d75,0x8000bd80,0xbd753c95,0x3d0e3d55,0x3d22bd46,0xbd6dbcc4,0xbbc93d7f,0x3d7bbc48,0xbcf1bd62,
0x3d353d35,0x3cf1bd62,0xbd7bbc48,0x3bc93d7f,0x3d6dbcc4,0xbd22bd46,0xbd0e3d55,0x3d753c95,0xbd800000,0x3c953d75,0x3d55bd0e,0xbd46bd22,0xbcc43d6d,0x3d7f3bc9,0xbc48bd7b,0xbd623cf1,
0x3d6d3cc4,0x3c95bd75,0xbd7bbc48,0xbbc93d7f,0x3d353d35,0x3d22bd46,0xbd55bd0e,0xbcf13d62,0x3cc43d6d,0x3d62bcf1,0xbd0ebd55,0xbd463d22,0x80003d80,0x3d7fbbc9,0xbc48bd7b,0xbd753c95,
0xbcc43d6d,0x3d753c95,0x3c48bd7b,0xbd7fbbc9,0xbd353d35,0x3d463d22,0x3d0ebd55,0xbd62bcf1,0xbd6d3cc4,0x3cf13d62,0x3d55bd0e,0xbd22bd46,0xbd800000,0x3bc93d7f,0x3d7bbc48,0xbc95bd75,
0x3d80,0x3d7f3bc9,0x3c48bd7b,0xbd75bc95,0xbcc43d6d,0x3d623cf1,0x3d0ebd55,0xbd46bd22,0xbd353d35,0x3d223d46,0x3d55bd0e,0xbcf1bd62,0xbd6d3cc4,0x3c953d75,0x3d7bbc48,0xbbc9bd7f,
0xbd800000,0xbbc93d7f,0x3d7b3c48,0x3c95bd75,0xbd6dbcc4,0xbcf13d62,0x3d553d0e,0x3d22bd46,0xbd35bd35,0xbd463d22,0x3d0e3d55,0x3d62bcf1,0xbcc4bd6d,0xbd753c95,0x3c483d7b,0x3d7fbbc9,
0xbd6d3cc4,0x3bc93d7f,0x3d7b3c48,0x3cf1bd62,0x3d80,0x3d753c95,0x3d0ebd55,0xbd22bd46,0x3cc4bd6d,0xbd46bd22,0xbd553d0e,0x3c953d75,0xbd35bd35,0xbd623cf1,0x3c483d7b,0x3d7f3bc9,
0x3cc43d6d,0x3d7fbbc9,0x3c48bd7b,0xbd62bcf1,0x3d800000,0x3c95bd75,0xbd55bd0e,0xbd463d22,0xbd6dbcc4,0xbd223d46,0x3d0e3d55,0x3d75bc95,0xbd353d35,0x3cf13d62,0x3d7bbc48,0x3bc9bd7f,
0x3d35bd35,0xbc95bd75,0xbd7bbc48,0xbd223d46,0x3cc43d6d,0x3d7f3bc9,0x3d0ebd55,0xbcf1bd62,0x3d80,0x3d623cf1,0x3d55bd0e,0xbbc9bd7f,0xbd6dbcc4,0xbd463d22,0x3c483d7b,0x3d753c95,
0x3d353d35,0x3d75bc95,0x3c48bd7b,0xbd46bd22,0xbd6d3cc4,0xbbc93d7f,0x3d553d0e,0x3d62bcf1,0xbd800000,0xbcf13d62,0x3d0e3d55,0x3d7fbbc9,0x3cc4bd6d,0xbd22bd46,0xbd7b3c48,0xbc953d75,
0xbd6dbcc4,0xbd623cf1,0xbc483d7b,0x3d223d46,0x3d353d35,0x3d7fbbc9,0x3d0ebd55,0xbc95bd75,0xbcc4bd6d,0xbd75bc95,0xbd553d0e,0xbbc93d7f,0x3d80,0x3d463d22,0x3d7bbc48,0x3cf1bd62,
0xbcc43d6d,0x3cf13d62,0x3d7b3c48,0x3d46bd22,0x3d35bd35,0xbbc9bd7f,0xbd55bd0e,0xbd753c95,0xbd6d3cc4,0xbc953d75,0x3d0e3d55,0x3d7f3bc9,0x3d800000,0x3d22bd46,0xbc48bd7b,0xbd62bcf1,
0xbd800000,0xbd463d22,0xbc483d7b,0x3cf13d62,0x3d6d3cc4,0x3d75bc95,0x3d0ebd55,0xbbc9bd7f,0xbd35bd35,0xbd7fbbc9,0xbd553d0e,0xbc953d75,0x3cc43d6d,0x3d623cf1,0x3d7bbc48,0x3d22bd46,
0x3d80,0x3d223d46,0x3d7b3c48,0x3d62bcf1,0x3cc4bd6d,0xbc95bd75,0xbd55bd0e,0xbd7f3bc9,0xbd353d35,0xbbc93d7f,0x3d0e3d55,0x3d753c95,0x3d6dbcc4,0x3cf1bd62,0xbc48bd7b,0xbd46bd22,
0xbcc4bd6d,0xbd46bd22,0xbd7bbc48,0xbd753c95,0x3d800000,0x3d62bcf1,0x3d0ebd55,0x3bc9bd7f,0x3d6d3cc4,0x3d7fbbc9,0x3d55bd0e,0x3cf1bd62,0xbd353d35,0xbc953d75,0x3c483d7b,0x3d223d46,
0x3d6dbcc4,0x3d22bd46,0x3c48bd7b,0xbc95bd75,0x3d80,0x3cf13d62,0x3d553d0e,0x3d7f3bc9,0xbcc43d6d,0x3bc93d7f,0x3d0e3d55,0x3d623cf1,0xbd35bd35,0xbd75bc95,0xbd7b3c48,0xbd463d22,
0x3d353d35,0x3d623cf1,0x3d7b3c48,0x3d7fbbc9,0x3d6dbcc4,0x3d46bd22,0x3d0ebd55,0x3c95bd75,0xbd800000,0xbd753c95,0xbd553d0e,0xbd223d46,0xbcc43d6d,0xbbc93d7f,0x3c483d7b,0x3cf13d62,
0x3d35bd35,0x3cf1bd62,0x3c48bd7b,0xbbc9bd7f,0xbcc4bd6d,0xbd22bd46,0xbd55bd0e,0xbd75bc95,0x3d80,0x3c953d75,0x3d0e3d55,0x3d463d22,0x3d6d3cc4,0x3d7f3bc9,0x3d7bbc48,0x3d62bcf1,
0x3cc4bd6d,0x3c95bd75,0x3c48bd7b,0x3bc9bd7f,0x3d35bd35,0x3d22bd46,0x3d0ebd55,0x3cf1bd62,0x3d6dbcc4,0x3d62bcf1,0x3d55bd0e,0x3d46bd22,0x3d800000,0x3d7fbbc9,0x3d7bbc48,0x3d75bc95,
0x3d6d3cc4,0x3d753c95,0x3d7b3c48,0x3d7f3bc9,0x3d353d35,0x3d463d22,0x3d553d0e,0x3d623cf1,0x3cc43d6d,0x3cf13d62,0x3d0e3d55,0x3d223d46,0x3d80,0x3bc93d7f,0x3c483d7b,0x3c953d75,
0xbd800000,0xbbc93d7f,0x3d7b3c48,0x3c95bd75,0xbd6dbcc4,0xbcf13d62,0x3d553d0e,0x3d22bd46,0xbd35bd35,0xbd463d22,0x3d0e3d55,0x3d62bcf1,0xbcc4bd6d,0xbd753c95,0x3c483d7b,0x3d7fbbc9,
0x8000bd80,0xbd7fbbc9,0xbc483d7b,0x3d753c95,0x3cc4bd6d,0xbd62bcf1,0xbd0e3d55,0x3d463d22,0x3d35bd35,0xbd22bd46,0xbd553d0e,0x3cf13d62,0x3d6dbcc4,0xbc95bd75,0xbd7b3c48,0x3bc93d7f,
0xbcc4bd6d,0xbd7f3bc9,0xbc483d7b,0x3d623cf1,0xbd800000,0xbc953d75,0x3d553d0e,0x3d46bd22,0x3d6d3cc4,0x3d22bd46,0xbd0ebd55,0xbd753c95,0x3d35bd35,0xbcf1bd62,0xbd7b3c48,0xbbc93d7f,
0xbd6d3cc4,0x3bc93d7f,0x3d7b3c48,0x3cf1bd62,0x80003d80,0x3d753c95,0x3d0ebd55,0xbd22bd46,0x3cc4bd6d,0xbd46bd22,0xbd553d0e,0x3c953d75,0xbd35bd35,0xbd623cf1,0x3c483d7b,0x3d7f3bc9,
0x3d353d35,0x3d75bc95,0x3c48bd7b,0xbd46bd22,0xbd6d3cc4,0xbbc93d7f,0x3d553d0e,0x3d62bcf1,0xbd800000,0xbcf13d62,0x3d0e3d55,0x3d7fbbc9,0x3cc4bd6d,0xbd22bd46,0xbd7b3c48,0xbc953d75,
0xbd353d35,0x3c953d75,0x3d7b3c48,0x3d22bd46,0xbcc4bd6d,0xbd7fbbc9,0xbd0e3d55,0x3cf13d62,0x8000bd80,0xbd62bcf1,0xbd553d0e,0x3bc93d7f,0x3d6d3cc4,0x3d46bd22,0xbc48bd7b,0xbd75bc95,
0x3cc4bd6d,0xbcf1bd62,0xbd7bbc48,0xbd463d22,0xbd353d35,0x3bc93d7f,0x3d553d0e,0x3d75bc95,0x3d6dbcc4,0x3c95bd75,0xbd0ebd55,0xbd7fbbc9,0xbd800000,0xbd223d46,0x3c483d7b,0x3d623cf1,
0xbd6dbcc4,0xbd623cf1,0xbc483d7b,0x3d223d46,0x3d353d35,0x3d7fbbc9,0x3d0ebd55,0xbc95bd75,0xbcc4bd6d,0xbd75bc95,0xbd553d0e,0xbbc93d7f,0x80003d80,0x3d463d22,0x3d7bbc48,0x3cf1bd62,
0x8000bd80,0xbd22bd46,0xbd7bbc48,0xbd623cf1,0xbcc43d6d,0x3c953d75,0x3d553d0e,0x3d7fbbc9,0x3d35bd35,0x3bc9bd7f,0xbd0ebd55,0xbd75bc95,0xbd6d3cc4,0xbcf13d62,0x3c483d7b,0x3d463d22,
0xbd800000,0xbd463d22,0xbc483d7b,0x3cf13d62,0x3d6d3cc4,0x3d75bc95,0x3d0ebd55,0xbbc9bd7f,0xbd35bd35,0xbd7fbbc9,0xbd553d0e,0xbc953d75,0x3cc43d6d,0x3d623cf1,0x3d7bbc48,0x3d22bd46,
0x3d6dbcc4,0x3d22bd46,0x3c48bd7b,0xbc95bd75,0x80003d80,0x3cf13d62,0x3d553d0e,0x3d7f3bc9,0xbcc43d6d,0x3bc93d7f,0x3d0e3d55,0x3d623cf1,0xbd35bd35,0xbd75bc95,0xbd7b3c48,0xbd463d22,
0x3cc43d6d,0x3d463d22,0x3d7b3c48,0x3d75bc95,0xbd800000,0xbd623cf1,0xbd0e3d55,0xbbc93d7f,0xbd6dbcc4,0xbd7f3bc9,0xbd553d0e,0xbcf13d62,0x3d35bd35,0x3c95bd75,0xbc48bd7b,0xbd22bd46,
0xbd353d35,0xbcf13d62,0xbc483d7b,0x3bc93d7f,0x3cc43d6d,0x3d223d46,0x3d553d0e,0x3d753c95,0x8000bd80,0xbc95bd75,0xbd0ebd55,0xbd46bd22,0xbd6dbcc4,0xbd7fbbc9,0xbd7b3c48,0xbd623cf1,
0x3d353d35,0x3d623cf1,0x3d7b3c48,0x3d7fbbc9,0x3d6dbcc4,0x3d46bd22,0x3d0ebd55,0x3c95bd75,0xbd800000,0xbd753c95,0xbd553d0e,0xbd223d46,0xbcc43d6d,0xbbc93d7f,0x3c483d7b,0x3cf13d62,
0x3d6d3cc4,0x3d753c95,0x3d7b3c48,0x3d7f3bc9,0x3d353d35,0x3d463d22,0x3d553d0e,0x3d623cf1,0x3cc43d6d,0x3cf13d62,0x3d0e3d55,0x3d223d46,0x80003d80,0x3bc93d7f,0x3c483d7b,0x3c953d75,
0xbcc43d6d,0xbc953d75,0xbc483d7b,0xbbc93d7f,0xbd353d35,0xbd223d46,0xbd0e3d55,0xbcf13d62,0xbd6d3cc4,0xbd623cf1,0xbd553d0e,0xbd463d22,0xbd800000,0xbd7f3bc9,0xbd7b3c48,0xbd753c95,
0x3d80,0xbc163d7d,0xbc953d75,0xbcdb3d67,0xbd0e3d55,0xbd2c3d3e,0xbd463d22,0xbd5c3d04,0xbd6d3cc4,0xbd783c79,0xbd7f3bc9,0xbd80bb49,0xbd7bbc48,0xbd71bcac,0xbd62bcf1,0xbd4ebd18,
0xbd35bd35,0xbd18bd4e,0xbcf1bd62,0xbcacbd71,0xbc48bd7b,0xbb49bd80,0x3bc9bd7f,0x3c79bd78,0x3cc4bd6d,0x3d04bd5c,0x3d22bd46,0x3d3ebd2c,0x3d55bd0e,0x3d67bcdb,0x3d75bc95,0x3d7dbc16,
0xbd7b3c48,0xbd7dbc16,0xbd62bcf1,0xbd2cbd3e,0x3d80,0xbcac3d71,0xbd223d46,0xbd5c3d04,0x3d55bd0e,0x3d78bc79,0x3d7f3bc9,0x3d673cdb,0xbcc4bd6d,0xbb49bd80,0x3c95bd75,0x3d18bd4e,
0xbd0e3d55,0xbd4e3d18,0xbd753c95,0xbd80bb49,0x3d353d35,0x3cdb3d67,0x3bc93d7f,0xbc793d78,0x3c48bd7b,0x3d04bd5c,0x3d46bd22,0x3d71bcac,0xbd6dbcc4,0xbd3ebd2c,0xbcf1bd62,0xbc16bd7d,
0x3d6dbcc4,0x3d7d3c16,0x3d463d22,0x3cac3d71,0xbc483d7b,0xbd2c3d3e,0xbd753c95,0xbd78bc79,0x3d80,0xbd043d5c,0xbd623cf1,0xbd80bb49,0xbd55bd0e,0xbcdbbd67,0x3bc9bd7f,0x3d18bd4e,
0xbcc43d6d,0xbd4e3d18,0xbd7f3bc9,0xbd67bcdb,0xbd0ebd55,0xbb49bd80,0x3cf1bd62,0x3d5cbd04,0xbd35bd35,0xbc79bd78,0x3c95bd75,0x3d3ebd2c,0x3d7bbc48,0x3d713cac,0x3d223d46,0x3c163d7d,
0xbd0ebd55,0x3c16bd7d,0x3d46bd22,0x3d803b49,0x3cc43d6d,0xbcac3d71,0xbd623cf1,0xbd78bc79,0xbc48bd7b,0x3d04bd5c,0x3d75bc95,0x3d673cdb,0x3d80,0xbd2c3d3e,0xbd7f3bc9,0xbd4ebd18,
0xbd7bbc48,0xbd18bd4e,0x3bc9bd7f,0x3d3ebd2c,0x3d6d3cc4,0x3cdb3d67,0xbc953d75,0xbd5c3d04,0xbd55bd0e,0xbc79bd78,0x3cf1bd62,0x3d71bcac,0x3d353d35,0x3b493d80,0xbd223d46,0xbd7d3c16,
0xbd35bd35,0x3c16bd7d,0x3d62bcf1,0x3d673cdb,0x3c483d7b,0xbd2c3d3e,0xbd7fbbc9,0xbd04bd5c,0x3cc4bd6d,0x3d78bc79,0x3d463d22,0xbb493d80,0xbd553d0e,0xbd71bcac,0xbc95bd75,0x3d18bd4e,
0x3d80,0xbd4e3d18,0xbd75bc95,0xbcacbd71,0x3d0ebd55,0x3d80bb49,0x3d223d46,0xbc793d78,0xbd6d3cc4,0xbd5cbd04,0xbbc9bd7f,0x3d3ebd2c,0x3d7b3c48,0x3cdb3d67,0xbcf13d62,0xbd7d3c16,
0x3d0ebd55,0x3d7d3c16,0x3c953d75,0xbd3e3d2c,0x3d353d35,0xbcac3d71,0xbd7f3bc9,0xbd04bd5c,0xbc483d7b,0xbd783c79,0xbd22bd46,0x3cdbbd67,0xbd6dbcc4,0xbb49bd80,0x3d62bcf1,0x3d4e3d18,
0x3d7bbc48,0x3d183d4e,0xbcf13d62,0xbd80bb49,0x3d80,0xbd673cdb,0xbd46bd22,0x3c79bd78,0xbd553d0e,0xbd5cbd04,0x3bc9bd7f,0x3d71bcac,0xbcc4bd6d,0x3d2cbd3e,0x3d753c95,0x3c163d7d,
0xbcc43d6d,0xbd7dbc16,0xbbc9bd7f,0x3d71bcac,0x3d0e3d55,0xbd2c3d3e,0xbd62bcf1,0x3c79bd78,0xbd35bd35,0x3d04bd5c,0x3d753c95,0xbb493d80,0xbd7b3c48,0xbcdbbd67,0x3d46bd22,0x3d4e3d18,
0x3d6dbcc4,0x3d183d4e,0xbd223d46,0xbd67bcdb,0x3c48bd7b,0x3d80bb49,0x3c953d75,0xbd5c3d04,0x3d80,0xbd783c79,0xbcf1bd62,0x3d3ebd2c,0x3d553d0e,0xbcac3d71,0xbd7fbbc9,0xbc16bd7d,
0x3d7b3c48,0xbc163d7d,0xbd7fbbc9,0x3b49bd80,0x3d6d3cc4,0xbcac3d71,0xbd75bc95,0x3c79bd78,0x3d553d0e,0xbd043d5c,0xbd62bcf1,0x3cdbbd67,0x3d353d35,0xbd2c3d3e,0xbd46bd22,0x3d18bd4e,
0x3d0e3d55,0xbd4e3d18,0xbd22bd46,0x3d3ebd2c,0x3cc43d6d,0xbd673cdb,0xbcf1bd62,0x3d5cbd04,0x3c483d7b,0xbd783c79,0xbc95bd75,0x3d71bcac,0x3d80,0xbd803b49,0xbbc9bd7f,0x3d7dbc16,
0xbd800000,0xbd7dbc16,0xbd75bc95,0xbd67bcdb,0xbd55bd0e,0xbd3ebd2c,0xbd22bd46,0xbd04bd5c,0xbcc4bd6d,0xbc79bd78,0xbbc9bd7f,0x3b49bd80,0x3c48bd7b,0x3cacbd71,0x3cf1bd62,0x3d18bd4e,
0x3d35bd35,0x3d4ebd18,0x3d62bcf1,0x3d71bcac,0x3d7bbc48,0x3d80bb49,0x3d7f3bc9,0x3d783c79,0x3d6d3cc4,0x3d5c3d04,0x3d463d22,0x3d2c3d3e,0x3d0e3d55,0x3cdb3d67,0x3c953d75,0x3c163d7d,
0xbc48bd7b,0x3c16bd7d,0x3cf1bd62,0x3d3ebd2c,0xbd800000,0xbd71bcac,0xbd46bd22,0xbd04bd5c,0x3d0e3d55,0x3c793d78,0xbbc93d7f,0xbcdb3d67,0x3d6dbcc4,0x3d80bb49,0x3d753c95,0x3d4e3d18,
0xbd55bd0e,0xbd18bd4e,0xbc95bd75,0x3b49bd80,0xbd353d35,0xbd673cdb,0xbd7f3bc9,0xbd78bc79,0x3d7b3c48,0x3d5c3d04,0x3d223d46,0x3cac3d71,0x3cc4bd6d,0x3d2cbd3e,0x3d62bcf1,0x3d7dbc16,
0x3cc43d6d,0xbc163d7d,0xbd223d46,0xbd713cac,0xbd7bbc48,0xbd3ebd2c,0xbc95bd75,0x3c79bd78,0xbd800000,0xbd5cbd04,0xbcf1bd62,0x3b49bd80,0x3d0ebd55,0x3d67bcdb,0x3d7f3bc9,0x3d4e3d18,
0xbd6dbcc4,0xbd18bd4e,0xbbc9bd7f,0x3cdbbd67,0x3d55bd0e,0x3d80bb49,0x3d623cf1,0x3d043d5c,0x3d35bd35,0x3d78bc79,0x3d753c95,0x3d2c3d3e,0x3c483d7b,0xbcac3d71,0xbd463d22,0xbd7d3c16,
0x3d55bd0e,0x3d7d3c16,0x3d223d46,0xbb493d80,0xbd6d3cc4,0xbd71bcac,0xbcf1bd62,0x3c79bd78,0x3d7bbc48,0x3d5c3d04,0x3c953d75,0xbcdb3d67,0xbd800000,0xbd3ebd2c,0xbbc9bd7f,0x3d18bd4e,
0x3c48bd7b,0x3d4ebd18,0x3d7f3bc9,0x3d2c3d3e,0xbcc43d6d,0xbd673cdb,0xbd75bc95,0xbd04bd5c,0x3d0ebd55,0x3d78bc79,0x3d623cf1,0x3cac3d71,0xbd353d35,0xbd803b49,0xbd46bd22,0xbc16bd7d,
0x3d35bd35,0x3d7d3c16,0x3cf13d62,0xbcdb3d67,0xbd7b3c48,0xbd3ebd2c,0x3bc9bd7f,0x3d5cbd04,0x3d6d3cc4,0x3c793d78,0xbd223d46,0xbd80bb49,0xbd0ebd55,0x3cacbd71,0x3d75bc95,0x3d4e3d18,
0xbd800000,0xbd18bd4e,0x3c95bd75,0x3d71bcac,0x3d553d0e,0x3b493d80,0xbd463d22,0xbd78bc79,0xbcc4bd6d,0x3d04bd5c,0x3d7fbbc9,0x3d2c3d3e,0xbc483d7b,0xbd673cdb,0xbd62bcf1,0xbc16bd7d,
0x3d553d0e,0xbc163d7d,0xbd753c95,0xbd2cbd3e,0xbd353d35,0xbd71bcac,0xbbc9bd7f,0x3d5cbd04,0xbd7bbc48,0xbc79bd78,0x3d46bd22,0x3d673cdb,0x3cc4bd6d,0x3d80bb49,0x3cf13d62,0xbd183d4e,
0x3c483d7b,0xbd4e3d18,0xbd62bcf1,0x3b49bd80,0xbd800000,0xbcdbbd67,0x3d22bd46,0x3d783c79,0xbd0ebd55,0x3d04bd5c,0x3d7f3bc9,0x3cac3d71,0x3d6dbcc4,0x3d3e3d2c,0xbc953d75,0xbd7d3c16,
0xbd6dbcc4,0x3c16bd7d,0x3d7fbbc9,0x3cac3d71,0xbd553d0e,0xbd3ebd2c,0x3cf1bd62,0x3d783c79,0x3d35bd35,0x3d5c3d04,0xbc953d75,0xbd80bb49,0xbc48bd7b,0x3d67bcdb,0x3d223d46,0xbd183d4e,
0x3cc43d6d,0xbd4e3d18,0xbd46bd22,0x3cdbbd67,0x3d7b3c48,0x3b493d80,0xbd753c95,0xbd04bd5c,0xbd800000,0xbc79bd78,0x3d62bcf1,0x3d2c3d3e,0xbd0e3d55,0xbd71bcac,0x3bc9bd7f,0x3d7dbc16,
0xbc483d7b,0xbd7dbc16,0x3bc9bd7f,0x3d803b49,0xbcc43d6d,0xbd71bcac,0x3c95bd75,0x3d783c79,0xbd0e3d55,0xbd5cbd04,0x3cf1bd62,0x3d673cdb,0xbd353d35,0xbd3ebd2c,0x3d22bd46,0x3d4e3d18,
0xbd553d0e,0xbd18bd4e,0x3d46bd22,0x3d2c3d3e,0xbd6d3cc4,0xbcdbbd67,0x3d62bcf1,0x3d043d5c,0xbd7b3c48,0xbc79bd78,0x3d75bc95,0x3cac3d71,0xbd800000,0xbb49bd80,0x3d7fbbc9,0x3c163d7d,
0x3d80,0xbd7dbc16,0x3c95bd75,0x3d673cdb,0xbd0e3d55,0xbd3ebd2c,0x3d46bd22,0x3d043d5c,0xbd6d3cc4,0xbc79bd78,0x3d7fbbc9,0xbb493d80,0xbd7bbc48,0x3cacbd71,0x3d623cf1,0xbd183d4e,
0xbd35bd35,0x3d4ebd18,0x3cf13d62,0xbd713cac,0xbc48bd7b,0x3d80bb49,0xbbc93d7f,0xbd78bc79,0x3cc4bd6d,0x3d5c3d04,0xbd223d46,0xbd2cbd3e,0x3d55bd0e,0x3cdb3d67,0xbd753c95,0xbc16bd7d,
0xbd7b3c48,0x3c16bd7d,0x3d623cf1,0xbd3e3d2c,0x3d80,0xbd71bcac,0x3d22bd46,0x3d043d5c,0x3d55bd0e,0x3c793d78,0xbd7fbbc9,0x3cdbbd67,0xbcc4bd6d,0x3d80bb49,0xbc953d75,0xbd4ebd18,
0xbd0e3d55,0xbd18bd4e,0x3d75bc95,0xbb493d80,0x3d353d35,0xbd673cdb,0xbbc9bd7f,0x3d783c79,0x3c48bd7b,0x3d5c3d04,0xbd463d22,0xbcacbd71,0xbd6dbcc4,0x3d2cbd3e,0x3cf13d62,0xbd7d3c16,
0x3d6dbcc4,0xbc163d7d,0xbd46bd22,0x3d71bcac,0xbc483d7b,0xbd3ebd2c,0x3d75bc95,0xbc793d78,0x3d80,0xbd5cbd04,0x3d62bcf1,0xbb493d80,0xbd55bd0e,0x3d67bcdb,0xbbc93d7f,0xbd4ebd18,
0xbcc43d6d,0xbd18bd4e,0x3d7fbbc9,0xbcdb3d67,0xbd0ebd55,0x3d80bb49,0xbcf13d62,0xbd04bd5c,0xbd35bd35,0x3d78bc79,0xbc953d75,0xbd2cbd3e,0x3d7bbc48,0xbcac3d71,0xbd22bd46,0x3d7dbc16,
0xbd0ebd55,0x3d7d3c16,0xbd463d22,0x3b49bd80,0x3cc43d6d,0xbd71bcac,0x3d62bcf1,0xbc793d78,0xbc48bd7b,0x3d5c3d04,0xbd753c95,0x3cdbbd67,0x3d80,0xbd3ebd2c,0x3d7fbbc9,0xbd183d4e,
0xbd7bbc48,0x3d4ebd18,0xbbc93d7f,0xbd2cbd3e,0x3d6d3cc4,0xbd673cdb,0x3c95bd75,0x3d043d5c,0xbd55bd0e,0x3d78bc79,0xbcf13d62,0xbcacbd71,0x3d353d35,0xbd803b49,0x3d22bd46,0x3c163d7d,
0xbd35bd35,0x3d7d3c16,0xbd623cf1,0x3cdbbd67,0x3c483d7b,0xbd3ebd2c,0x3d7f3bc9,0xbd5c3d04,0x3cc4bd6d,0x3c793d78,0xbd46bd22,0x3d803b49,0xbd553d0e,0x3cacbd71,0x3c953d75,0xbd4ebd18,
0x3d80,0xbd18bd4e,0x3d753c95,0xbd713cac,0x3d0ebd55,0x3b493d80,0xbd22bd46,0x3d783c79,0xbd6d3cc4,0x3d04bd5c,0x3bc93d7f,0xbd2cbd3e,0x3d7b3c48,0xbd673cdb,0x3cf1bd62,0x3c163d7d,
0x3d0ebd55,0xbc163d7d,0xbc95bd75,0x3d2c3d3e,0x3d353d35,0xbd71bcac,0x3d7fbbc9,0xbd5c3d04,0xbc483d7b,0xbc79bd78,0x3d223d46,0xbd67bcdb,0xbd6dbcc4,0x3d80bb49,0xbd623cf1,0x3d18bd4e,
0x3d7bbc48,0xbd4e3d18,0x3cf1bd62,0xbb493d80,0x3d80,0xbcdbbd67,0x3d463d22,0xbd78bc79,0xbd553d0e,0x3d04bd5c,0xbbc93d7f,0xbcacbd71,0xbcc4bd6d,0x3d3e3d2c,0xbd75bc95,0x3d7dbc16,
0xbcc43d6d,0x3c16bd7d,0x3bc93d7f,0xbcacbd71,0x3d0e3d55,0xbd3ebd2c,0x3d623cf1,0xbd78bc79,0xbd35bd35,0x3d5c3d04,0xbd75bc95,0x3d803b49,0xbd7b3c48,0x3d67bcdb,0xbd463d22,0x3d18bd4e,
0x3d6dbcc4,0xbd4e3d18,0x3d22bd46,0xbcdb3d67,0x3c48bd7b,0x3b493d80,0xbc95bd75,0x3d043d5c,0x3d80,0xbc79bd78,0x3cf13d62,0xbd2cbd3e,0x3d553d0e,0xbd71bcac,0x3d7f3bc9,0xbd7d3c16,
0x3d7b3c48,0xbd7dbc16,0x3d7f3bc9,0xbd80bb49,0x3d6d3cc4,0xbd71bcac,0x3d753c95,0xbd78bc79,0x3d553d0e,0xbd5cbd04,0x3d623cf1,0xbd67bcdb,0x3d353d35,0xbd3ebd2c,0x3d463d22,0xbd4ebd18,
0x3d0e3d55,0xbd18bd4e,0x3d223d46,0xbd2cbd3e,0x3cc43d6d,0xbcdbbd67,0x3cf13d62,0xbd04bd5c,0x3c483d7b,0xbc79bd78,0x3c953d75,0xbcacbd71,0x3d80,0xbb49bd80,0x3bc93d7f,0xbc16bd7d,
0xbd800000,0x3c16bd7d,0x3d753c95,0xbcdb3d67,0xbd55bd0e,0x3d2cbd3e,0x3d223d46,0xbd5c3d04,0xbcc4bd6d,0x3d78bc79,0x3bc93d7f,0xbd80bb49,0x3c48bd7b,0x3d713cac,0xbcf13d62,0xbd4ebd18,
0x3d35bd35,0x3d183d4e,0xbd623cf1,0xbcacbd71,0x3d7bbc48,0x3b493d80,0xbd7fbbc9,0x3c79bd78,0x3d6d3cc4,0xbd043d5c,0xbd46bd22,0x3d3ebd2c,0x3d0e3d55,0xbd673cdb,0xbc95bd75,0x3d7dbc16,
0xbc48bd7b,0x3d7d3c16,0xbcf13d62,0xbd2cbd3e,0xbd800000,0x3cacbd71,0x3d463d22,0xbd5c3d04,0x3d0e3d55,0xbd783c79,0x3bc9bd7f,0x3d673cdb,0x3d6dbcc4,0x3b493d80,0xbd75bc95,0x3d18bd4e,
0xbd55bd0e,0x3d4ebd18,0x3c953d75,0xbd80bb49,0xbd353d35,0xbcdbbd67,0x3d7fbbc9,0xbc793d78,0x3d7b3c48,0xbd043d5c,0xbd22bd46,0x3d71bcac,0x3cc4bd6d,0x3d3e3d2c,0xbd623cf1,0xbc16bd7d,
0x3cc43d6d,0xbd7dbc16,0x3d22bd46,0x3cac3d71,0xbd7bbc48,0x3d2cbd3e,0x3c953d75,0xbd78bc79,0xbd800000,0x3d04bd5c,0x3cf13d62,0xbd80bb49,0x3d0ebd55,0x3cdb3d67,0xbd7fbbc9,0x3d18bd4e,
0xbd6dbcc4,0x3d4ebd18,0x3bc93d7f,0xbd67bcdb,0x3d55bd0e,0x3b493d80,0xbd62bcf1,0x3d5cbd04,0x3d35bd35,0x3c793d78,0xbd75bc95,0x3d3ebd2c,0x3c483d7b,0xbd71bcac,0x3d46bd22,0x3c163d7d,
0x3d55bd0e,0xbc163d7d,0xbd22bd46,0x3d803b49,0xbd6d3cc4,0x3cacbd71,0x3cf13d62,0xbd78bc79,0x3d7bbc48,0xbd043d5c,0xbc95bd75,0x3d673cdb,0xbd800000,0x3d2cbd3e,0x3bc93d7f,0xbd4ebd18,
0x3c48bd7b,0x3d183d4e,0xbd7fbbc9,0x3d3ebd2c,0xbcc43d6d,0xbcdbbd67,0x3d753c95,0xbd5c3d04,0x3d0ebd55,0x3c793d78,0xbd62bcf1,0x3d71bcac,0xbd353d35,0xbb49bd80,0x3d463d22,0xbd7d3c16,
0x3d35bd35,0xbc163d7d,0xbcf1bd62,0x3d673cdb,0xbd7b3c48,0x3d2cbd3e,0xbbc93d7f,0xbd04bd5c,0x3d6d3cc4,0xbd783c79,0x3d22bd46,0xbb493d80,0xbd0ebd55,0x3d713cac,0xbd753c95,0x3d18bd4e,
0xbd800000,0x3d4ebd18,0xbc953d75,0xbcacbd71,0x3d553d0e,0xbd803b49,0x3d46bd22,0xbc793d78,0xbcc4bd6d,0x3d5c3d04,0xbd7f3bc9,0x3d3ebd2c,0xbc483d7b,0xbcdbbd67,0x3d623cf1,0xbd7d3c16,
0x3d553d0e,0xbd7dbc16,0x3d75bc95,0xbd3e3d2c,0xbd353d35,0x3cacbd71,0x3bc93d7f,0xbd04bd5c,0xbd7bbc48,0x3d78bc79,0xbd463d22,0x3cdbbd67,0x3cc4bd6d,0x3b493d80,0xbcf1bd62,0x3d4e3d18,
0x3c483d7b,0xbd18bd4e,0x3d623cf1,0xbd80bb49,0xbd800000,0x3d67bcdb,0xbd223d46,0x3c79bd78,0xbd0ebd55,0x3d5c3d04,0xbd7fbbc9,0x3d71bcac,0x3d6dbcc4,0xbd2c3d3e,0x3c95bd75,0x3c163d7d,
0xbd6dbcc4,0x3d7d3c16,0xbd7f3bc9,0x3d71bcac,0xbd553d0e,0x3d2cbd3e,0xbcf13d62,0x3c79bd78,0x3d35bd35,0xbd043d5c,0x3c95bd75,0xbb493d80,0xbc48bd7b,0x3cdb3d67,0xbd22bd46,0x3d4e3d18,
0x3cc43d6d,0xbd18bd4e,0x3d463d22,0xbd67bcdb,0x3d7b3c48,0xbd803b49,0x3d75bc95,0xbd5c3d04,0xbd800000,0x3d78bc79,0xbd623cf1,0x3d3ebd2c,0xbd0e3d55,0x3cacbd71,0xbbc93d7f,0xbc16bd7d,
0xbc483d7b,0x3c16bd7d,0xbbc93d7f,0x3b49bd80,0xbcc43d6d,0x3cacbd71,0xbc953d75,0x3c79bd78,0xbd0e3d55,0x3d04bd5c,0xbcf13d62,0x3cdbbd67,0xbd353d35,0x3d2cbd3e,0xbd223d46,0x3d18bd4e,
0xbd553d0e,0x3d4ebd18,0xbd463d22,0x3d3ebd2c,0xbd6d3cc4,0x3d67bcdb,0xbd623cf1,0x3d5cbd04,0xbd7b3c48,0x3d78bc79,0xbd753c95,0x3d71bcac,0xbd800000,0x3d80bb49,0xbd7f3bc9,0x3d7dbc16,
0x3d80,0x3c16bd7d,0xbc953d75,0x3cdbbd67,0xbd0e3d55,0x3d2cbd3e,0xbd463d22,0x3d5cbd04,0xbd6d3cc4,0x3d78bc79,0xbd7f3bc9,0x3d803b49,0xbd7bbc48,0x3d713cac,0xbd62bcf1,0x3d4e3d18,
0xbd35bd35,0x3d183d4e,0xbcf1bd62,0x3cac3d71,0xbc48bd7b,0x3b493d80,0x3bc9bd7f,0xbc793d78,0x3cc4bd6d,0xbd043d5c,0x3d22bd46,0xbd3e3d2c,0x3d55bd0e,0xbd673cdb,0x3d75bc95,0xbd7d3c16,
0xbd7b3c48,0x3d7d3c16,0xbd62bcf1,0x3d2c3d3e,0x3d80,0x3cacbd71,0xbd223d46,0x3d5cbd04,0x3d55bd0e,0xbd783c79,0x3d7f3bc9,0xbd67bcdb,0xbcc4bd6d,0x3b493d80,0x3c95bd75,0xbd183d4e,
0xbd0e3d55,0x3d4ebd18,0xbd753c95,0x3d803b49,0x3d353d35,0xbcdbbd67,0x3bc93d7f,0x3c79bd78,0x3c48bd7b,0xbd043d5c,0x3d46bd22,0xbd713cac,0xbd6dbcc4,0x3d3e3d2c,0xbcf1bd62,0x3c163d7d,
0x3d6dbcc4,0xbd7dbc16,0x3d463d22,0xbcacbd71,0xbc483d7b,0x3d2cbd3e,0xbd753c95,0x3d783c79,0x3d80,0x3d04bd5c,0xbd623cf1,0x3d803b49,0xbd55bd0e,0x3cdb3d67,0x3bc9bd7f,0xbd183d4e,
0xbcc43d6d,0x3d4ebd18,0xbd7f3bc9,0x3d673cdb,0xbd0ebd55,0x3b493d80,0x3cf1bd62,0xbd5c3d04,0xbd35bd35,0x3c793d78,0x3c95bd75,0xbd3e3d2c,0x3d7bbc48,0xbd71bcac,0x3d223d46,0xbc16bd7d,
0xbd0ebd55,0xbc163d7d,0x3d46bd22,0xbd80bb49,0x3cc43d6d,0x3cacbd71,0xbd623cf1,0x3d783c79,0xbc48bd7b,0xbd043d5c,0x3d75bc95,0xbd67bcdb,0x3d80,0x3d2cbd3e,0xbd7f3bc9,0x3d4e3d18,
0xbd7bbc48,0x3d183d4e,0x3bc9bd7f,0xbd3e3d2c,0x3d6d3cc4,0xbcdbbd67,0xbc953d75,0x3d5cbd04,0xbd55bd0e,0x3c793d78,0x3cf1bd62,0xbd713cac,0x3d353d35,0xbb49bd80,0xbd223d46,0x3d7dbc16,
0xbd35bd35,0xbc163d7d,0x3d62bcf1,0xbd67bcdb,0x3c483d7b,0x3d2cbd3e,0xbd7fbbc9,0x3d043d5c,0x3cc4bd6d,0xbd783c79,0x3d463d22,0x3b49bd80,0xbd553d0e,0x3d713cac,0xbc95bd75,0xbd183d4e,
0x3d80,0x3d4ebd18,0xbd75bc95,0x3cac3d71,0x3d0ebd55,0xbd803b49,0x3d223d46,0x3c79bd78,0xbd6d3cc4,0x3d5c3d04,0xbbc9bd7f,0xbd3e3d2c,0x3d7b3c48,0xbcdbbd67,0xbcf13d62,0x3d7dbc16,
0x3d0ebd55,0xbd7dbc16,0x3c953d75,0x3d3ebd2c,0x3d353d35,0x3cacbd71,0xbd7f3bc9,0x3d043d5c,0xbc483d7b,0x3d78bc79,0xbd22bd46,0xbcdb3d67,0xbd6dbcc4,0x3b493d80,0x3d62bcf1,0xbd4ebd18,
0x3d7bbc48,0xbd18bd4e,0xbcf13d62,0x3d803b49,0x3d80,0x3d67bcdb,0xbd46bd22,0xbc793d78,0xbd553d0e,0x3d5c3d04,0x3bc9bd7f,0xbd713cac,0xbcc4bd6d,0xbd2c3d3e,0x3d753c95,0xbc16bd7d,
0xbcc43d6d,0x3d7d3c16,0xbbc9bd7f,0xbd713cac,0x3d0e3d55,0x3d2cbd3e,0xbd62bcf1,0xbc793d78,0xbd35bd35,0xbd043d5c,0x3d753c95,0x3b49bd80,0xbd7b3c48,0x3cdb3d67,0x3d46bd22,0xbd4ebd18,
0x3d6dbcc4,0xbd18bd4e,0xbd223d46,0x3d673cdb,0x3c48bd7b,0xbd803b49,0x3c953d75,0x3d5cbd04,0x3d80,0x3d78bc79,0xbcf1bd62,0xbd3e3d2c,0x3d553d0e,0x3cacbd71,0xbd7fbbc9,0x3c163d7d,
0x3d7b3c48,0x3c16bd7d,0xbd7fbbc9,0xbb493d80,0x3d6d3cc4,0x3cacbd71,0xbd75bc95,0xbc793d78,0x3d553d0e,0x3d04bd5c,0xbd62bcf1,0xbcdb3d67,0x3d353d35,0x3d2cbd3e,0xbd46bd22,0xbd183d4e,
0x3d0e3d55,0x3d4ebd18,0xbd22bd46,0xbd3e3d2c,0x3cc43d6d,0x3d67bcdb,0xbcf1bd62,0xbd5c3d04,0x3c483d7b,0x3d78bc79,0xbc95bd75,0xbd713cac,0x3d80,0x3d80bb49,0xbbc9bd7f,0xbd7d3c16,
0xbd800000,0x3d7d3c16,0xbd75bc95,0x3d673cdb,0xbd55bd0e,0x3d3e3d2c,0xbd22bd46,0x3d043d5c,0xbcc4bd6d,0x3c793d78,0xbbc9bd7f,0xbb493d80,0x3c48bd7b,0xbcac3d71,0x3cf1bd62,0xbd183d4e,
0x3d35bd35,0xbd4e3d18,0x3d62bcf1,0xbd713cac,0x3d7bbc48,0xbd803b49,0x3d7f3bc9,0xbd78bc79,0x3d6d3cc4,0xbd5cbd04,0x3d463d22,0xbd2cbd3e,0x3d0e3d55,0xbcdbbd67,0x3c953d75,0xbc16bd7d,
0xbc48bd7b,0xbc163d7d,0x3cf1bd62,0xbd3e3d2c,0xbd800000,0x3d713cac,0xbd46bd22,0x3d043d5c,0x3d0e3d55,0xbc79bd78,0xbbc93d7f,0x3cdbbd67,0x3d6dbcc4,0xbd803b49,0x3d753c95,0xbd4ebd18,
0xbd55bd0e,0x3d183d4e,0xbc95bd75,0xbb493d80,0xbd353d35,0x3d67bcdb,0xbd7f3bc9,0x3d783c79,0x3d7b3c48,0xbd5cbd04,0x3d223d46,0xbcacbd71,0x3cc4bd6d,0xbd2c3d3e,0x3d62bcf1,0xbd7d3c16,
0x3cc43d6d,0x3c16bd7d,0xbd223d46,0x3d71bcac,0xbd7bbc48,0x3d3e3d2c,0xbc95bd75,0xbc793d78,0xbd800000,0x3d5c3d04,0xbcf1bd62,0xbb493d80,0x3d0ebd55,0xbd673cdb,0x3d7f3bc9,0xbd4ebd18,
0xbd6dbcc4,0x3d183d4e,0xbbc9bd7f,0xbcdb3d67,0x3d55bd0e,0xbd803b49,0x3d623cf1,0xbd04bd5c,0x3d35bd35,0xbd783c79,0x3d753c95,0xbd2cbd3e,0x3c483d7b,0x3cacbd71,0xbd463d22,0x3d7dbc16,
0x3d55bd0e,0xbd7dbc16,0x3d223d46,0x3b49bd80,0xbd6d3cc4,0x3d713cac,0xbcf1bd62,0xbc793d78,0x3d7bbc48,0xbd5cbd04,0x3c953d75,0x3cdbbd67,0xbd800000,0x3d3e3d2c,0xbbc9bd7f,0xbd183d4e,
0x3c48bd7b,0xbd4e3d18,0x3d7f3bc9,0xbd2cbd3e,0xbcc43d6d,0x3d67bcdb,0xbd75bc95,0x3d043d5c,0x3d0ebd55,0xbd783c79,0x3d623cf1,0xbcacbd71,0xbd353d35,0x3d80bb49,0xbd46bd22,0x3c163d7d,
0x3d35bd35,0xbd7dbc16,0x3cf13d62,0x3cdbbd67,0xbd7b3c48,0x3d3e3d2c,0x3bc9bd7f,0xbd5c3d04,0x3d6d3cc4,0xbc79bd78,0xbd223d46,0x3d803b49,0xbd0ebd55,0xbcac3d71,0x3d75bc95,0xbd4ebd18,
0xbd800000,0x3d183d4e,0x3c95bd75,0xbd713cac,0x3d553d0e,0xbb49bd80,0xbd463d22,0x3d783c79,0xbcc4bd6d,0xbd043d5c,0x3d7fbbc9,0xbd2cbd3e,0xbc483d7b,0x3d67bcdb,0xbd62bcf1,0x3c163d7d,
0x3d553d0e,0x3c16bd7d,0xbd753c95,0x3d2c3d3e,0xbd353d35,0x3d713cac,0xbbc9bd7f,0xbd5c3d04,0xbd7bbc48,0x3c793d78,0x3d46bd22,0xbd67bcdb,0x3cc4bd6d,0xbd803b49,0x3cf13d62,0x3d18bd4e,
0x3c483d7b,0x3d4ebd18,0xbd62bcf1,0xbb493d80,0xbd800000,0x3cdb3d67,0x3d22bd46,0xbd78bc79,0xbd0ebd55,0xbd043d5c,0x3d7f3bc9,0xbcacbd71,0x3d6dbcc4,0xbd3ebd2c,0xbc953d75,0x3d7dbc16,
0xbd6dbcc4,0xbc163d7d,0x3d7fbbc9,0xbcacbd71,0xbd553d0e,0x3d3e3d2c,0x3cf1bd62,0xbd78bc79,0x3d35bd35,0xbd5cbd04,0xbc953d75,0x3d803b49,0xbc48bd7b,0xbd673cdb,0x3d223d46,0x3d18bd4e,
0x3cc43d6d,0x3d4ebd18,0xbd46bd22,0xbcdb3d67,0x3d7b3c48,0xbb49bd80,0xbd753c95,0x3d043d5c,0xbd800000,0x3c793d78,0x3d62bcf1,0xbd2cbd3e,0xbd0e3d55,0x3d713cac,0x3bc9bd7f,0xbd7d3c16,
0xbc483d7b,0x3d7d3c16,0x3bc9bd7f,0xbd80bb49,0xbcc43d6d,0x3d713cac,0x3c95bd75,0xbd78bc79,0xbd0e3d55,0x3d5c3d04,0x3cf1bd62,0xbd67bcdb,0xbd353d35,0x3d3e3d2c,0x3d22bd46,0xbd4ebd18,
0xbd553d0e,0x3d183d4e,0x3d46bd22,0xbd2cbd3e,0xbd6d3cc4,0x3cdb3d67,0x3d62bcf1,0xbd04bd5c,0xbd7b3c48,0x3c793d78,0x3d75bc95,0xbcacbd71,0xbd800000,0x3b493d80,0x3d7fbbc9,0xbc16bd7d,
0x3d80,0x3d7d3c16,0x3c95bd75,0xbd67bcdb,0xbd0e3d55,0x3d3e3d2c,0x3d46bd22,0xbd04bd5c,0xbd6d3cc4,0x3c793d78,0x3d7fbbc9,0x3b49bd80,0xbd7bbc48,0xbcac3d71,0x3d623cf1,0x3d18bd4e,
0xbd35bd35,0xbd4e3d18,0x3cf13d62,0x3d71bcac,0xbc48bd7b,0xbd803b49,0xbbc93d7f,0x3d783c79,0x3cc4bd6d,0xbd5cbd04,0xbd223d46,0x3d2c3d3e,0x3d55bd0e,0xbcdbbd67,0xbd753c95,0x3c163d7d,
0xbd7b3c48,0xbc163d7d,0x3d623cf1,0x3d3ebd2c,0x3d80,0x3d713cac,0x3d22bd46,0xbd04bd5c,0x3d55bd0e,0xbc79bd78,0xbd7fbbc9,0xbcdb3d67,0xbcc4bd6d,0xbd803b49,0xbc953d75,0x3d4e3d18,
0xbd0e3d55,0x3d183d4e,0x3d75bc95,0x3b49bd80,0x3d353d35,0x3d67bcdb,0xbbc9bd7f,0xbd78bc79,0x3c48bd7b,0xbd5cbd04,0xbd463d22,0x3cac3d71,0xbd6dbcc4,0xbd2c3d3e,0x3cf13d62,0x3d7dbc16,
0x3d6dbcc4,0x3c16bd7d,0xbd46bd22,0xbd713cac,0xbc483d7b,0x3d3e3d2c,0x3d75bc95,0x3c79bd78,0x3d80,0x3d5c3d04,0x3d62bcf1,0x3b49bd80,0xbd55bd0e,0xbd673cdb,0xbbc93d7f,0x3d4e3d18,
0xbcc43d6d,0x3d183d4e,0x3d7fbbc9,0x3cdbbd67,0xbd0ebd55,0xbd803b49,0xbcf13d62,0x3d043d5c,0xbd35bd35,0xbd783c79,0xbc953d75,0x3d2c3d3e,0x3d7bbc48,0x3cacbd71,0xbd22bd46,0xbd7d3c16,
0xbd0ebd55,0xbd7dbc16,0xbd463d22,0xbb493d80,0x3cc43d6d,0x3d713cac,0x3d62bcf1,0x3c79bd78,0xbc48bd7b,0xbd5cbd04,0xbd753c95,0xbcdb3d67,0x3d80,0x3d3e3d2c,0x3d7fbbc9,0x3d18bd4e,
0xbd7bbc48,0xbd4e3d18,0xbbc93d7f,0x3d2c3d3e,0x3d6d3cc4,0x3d67bcdb,0x3c95bd75,0xbd04bd5c,0xbd55bd0e,0xbd783c79,0xbcf13d62,0x3cac3d71,0x3d353d35,0x3d80bb49,0x3d22bd46,0xbc16bd7d,
0xbd35bd35,0xbd7dbc16,0xbd623cf1,0xbcdb3d67,0x3c483d7b,0x3d3e3d2c,0x3d7f3bc9,0x3d5cbd04,0x3cc4bd6d,0xbc79bd78,0xbd46bd22,0xbd80bb49,0xbd553d0e,0xbcac3d71,0x3c953d75,0x3d4e3d18,
0x3d80,0x3d183d4e,0x3d753c95,0x3d71bcac,0x3d0ebd55,0xbb49bd80,0xbd22bd46,0xbd78bc79,0xbd6d3cc4,0xbd043d5c,0x3bc93d7f,0x3d2c3d3e,0x3d7b3c48,0x3d67bcdb,0x3cf1bd62,0xbc16bd7d,
0x3d0ebd55,0x3c16bd7d,0xbc95bd75,0xbd2cbd3e,0x3d353d35,0x3d713cac,0x3d7fbbc9,0x3d5cbd04,0xbc483d7b,0x3c793d78,0x3d223d46,0x3d673cdb,0xbd6dbcc4,0xbd803b49,0xbd623cf1,0xbd183d4e,
0x3d7bbc48,0x3d4ebd18,0x3cf1bd62,0x3b49bd80,0x3d80,0x3cdb3d67,0x3d463d22,0x3d783c79,0xbd553d0e,0xbd043d5c,0xbbc93d7f,0x3cac3d71,0xbcc4bd6d,0xbd3ebd2c,0xbd75bc95,0xbd7d3c16,
0xbcc43d6d,0xbc163d7d,0x3bc93d7f,0x3cac3d71,0x3d0e3d55,0x3d3e3d2c,0x3d623cf1,0x3d783c79,0xbd35bd35,0xbd5cbd04,0xbd75bc95,0xbd80bb49,0xbd7b3c48,0xbd673cdb,0xbd463d22,0xbd183d4e,
0x3d6dbcc4,0x3d4ebd18,0x3d22bd46,0x3cdbbd67,0x3c48bd7b,0xbb49bd80,0xbc95bd75,0xbd04bd5c,0x3d80,0x3c793d78,0x3cf13d62,0x3d2c3d3e,0x3d553d0e,0x3d713cac,0x3d7f3bc9,0x3d7dbc16,
0x3d7b3c48,0x3d7d3c16,0x3d7f3bc9,0x3d803b49,0x3d6d3cc4,0x3d713cac,0x3d753c95,0x3d783c79,0x3d553d0e,0x3d5c3d04,0x3d623cf1,0x3d673cdb,0x3d353d35,0x3d3e3d2c,0x3d463d22,0x3d4e3d18,
0x3d0e3d55,0x3d183d4e,0x3d223d46,0x3d2c3d3e,0x3cc43d6d,0x3cdb3d67,0x3cf13d62,0x3d043d5c,0x3c483d7b,0x3c793d78,0x3c953d75,0x3cac3d71,0x3d80,0x3b493d80,0x3bc93d7f,0x3c163d7d,
0xbd800000,0xbc163d7d,0x3d753c95,0x3cdbbd67,0xbd55bd0e,0xbd2c3d3e,0x3d223d46,0x3d5cbd04,0xbcc4bd6d,0xbd783c79,0x3bc93d7f,0x3d803b49,0x3c48bd7b,0xbd71bcac,0xbcf13d62,0x3d4e3d18,
0x3d35bd35,0xbd18bd4e,0xbd623cf1,0x3cac3d71,0x3d7bbc48,0xbb49bd80,0xbd7fbbc9,0xbc793d78,0x3d6d3cc4,0x3d04bd5c,0xbd46bd22,0xbd3e3d2c,0x3d0e3d55,0x3d67bcdb,0xbc95bd75,0xbd7d3c16,
0xbc48bd7b,0xbd7dbc16,0xbcf13d62,0x3d2c3d3e,0xbd800000,0xbcac3d71,0x3d463d22,0x3d5cbd04,0x3d0e3d55,0x3d78bc79,0x3bc9bd7f,0xbd67bcdb,0x3d6dbcc4,0xbb49bd80,0xbd75bc95,0xbd183d4e,
0xbd55bd0e,0xbd4e3d18,0x3c953d75,0x3d803b49,0xbd353d35,0x3cdb3d67,0x3d7fbbc9,0x3c79bd78,0x3d7b3c48,0x3d04bd5c,0xbd22bd46,0xbd713cac,0x3cc4bd6d,0xbd3ebd2c,0xbd623cf1,0x3c163d7d,
0x3cc43d6d,0x3d7d3c16,0x3d22bd46,0xbcacbd71,0xbd7bbc48,0xbd2c3d3e,0x3c953d75,0x3d783c79,0xbd800000,0xbd043d5c,0x3cf13d62,0x3d803b49,0x3d0ebd55,0xbcdbbd67,0xbd7fbbc9,0xbd183d4e,
0xbd6dbcc4,0xbd4e3d18,0x3bc93d7f,0x3d673cdb,0x3d55bd0e,0xbb49bd80,0xbd62bcf1,0xbd5c3d04,0x3d35bd35,0xbc79bd78,0xbd75bc95,0xbd3e3d2c,0x3c483d7b,0x3d713cac,0x3d46bd22,0xbc16bd7d,
0x3d55bd0e,0x3c16bd7d,0xbd22bd46,0xbd80bb49,0xbd6d3cc4,0xbcac3d71,0x3cf13d62,0x3d783c79,0x3d7bbc48,0x3d04bd5c,0xbc95bd75,0xbd67bcdb,0xbd800000,0xbd2c3d3e,0x3bc93d7f,0x3d4e3d18,
0x3c48bd7b,0xbd18bd4e,0xbd7fbbc9,0xbd3e3d2c,0xbcc43d6d,0x3cdb3d67,0x3d753c95,0x3d5cbd04,0x3d0ebd55,0xbc79bd78,0xbd62bcf1,0xbd713cac,0xbd353d35,0x3b493d80,0x3d463d22,0x3d7dbc16,
0x3d35bd35,0x3c16bd7d,0xbcf1bd62,0xbd67bcdb,0xbd7b3c48,0xbd2c3d3e,0xbbc93d7f,0x3d043d5c,0x3d6d3cc4,0x3d78bc79,0x3d22bd46,0x3b49bd80,0xbd0ebd55,0xbd71bcac,0xbd753c95,0xbd183d4e,
0xbd800000,0xbd4e3d18,0xbc953d75,0x3cac3d71,0x3d553d0e,0x3d80bb49,0x3d46bd22,0x3c79bd78,0xbcc4bd6d,0xbd5cbd04,0xbd7f3bc9,0xbd3e3d2c,0xbc483d7b,0x3cdb3d67,0x3d623cf1,0x3d7dbc16,
0x3d553d0e,0x3d7d3c16,0x3d75bc95,0x3d3ebd2c,0xbd353d35,0xbcac3d71,0x3bc93d7f,0x3d043d5c,0xbd7bbc48,0xbd783c79,0xbd463d22,0xbcdb3d67,0x3cc4bd6d,0xbb49bd80,0xbcf1bd62,0xbd4ebd18,
0x3c483d7b,0x3d183d4e,0x3d623cf1,0x3d803b49,0xbd800000,0xbd673cdb,0xbd223d46,0xbc793d78,0xbd0ebd55,0xbd5cbd04,0xbd7fbbc9,0xbd713cac,0x3d6dbcc4,0x3d2cbd3e,0x3c95bd75,0xbc16bd7d,
0xbd6dbcc4,0xbd7dbc16,0xbd7f3bc9,0xbd713cac,0xbd553d0e,0xbd2c3d3e,0xbcf13d62,0xbc793d78,0x3d35bd35,0x3d04bd5c,0x3c95bd75,0x3b49bd80,0xbc48bd7b,0xbcdbbd67,0xbd22bd46,0xbd4ebd18,
0x3cc43d6d,0x3d183d4e,0x3d463d22,0x3d673cdb,0x3d7b3c48,0x3d80bb49,0x3d75bc95,0x3d5cbd04,0xbd800000,0xbd783c79,0xbd623cf1,0xbd3e3d2c,0xbd0e3d55,0xbcac3d71,0xbbc93d7f,0x3c163d7d,
0xbc483d7b,0xbc163d7d,0xbbc93d7f,0xbb493d80,0xbcc43d6d,0xbcac3d71,0xbc953d75,0xbc793d78,0xbd0e3d55,0xbd043d5c,0xbcf13d62,0xbcdb3d67,0xbd353d35,0xbd2c3d3e,0xbd223d46,0xbd183d4e,
0xbd553d0e,0xbd4e3d18,0xbd463d22,0xbd3e3d2c,0xbd6d3cc4,0xbd673cdb,0xbd623cf1,0xbd5c3d04,0xbd7b3c48,0xbd783c79,0xbd753c95,0xbd713cac,0xbd800000,0xbd803b49,0xbd7f3bc9,0xbd7d3c16,
0x3f003f00,0xbf003f00,0x3f003f00,0xbf003f00,0x3f003f00,0xbf003f00,0x3f003f00,0xbf003f00,0x3f003f00,0xbf003f00,0x3f003f00,0xbf003f00,0x3f003f00,0xbf003f00,0x3f003f00,0xbf003f00,
0x3eff3f00,0xbd490000,0x3ea23eb5,0xbec6beb5,0x3ef53efb,0xbe15bdc8,0x3e713e8e,0xbee2bed5,0x3ee23eed,0xbe71be44,0x3e153e44,0xbef5beed,0x3ec63ed5,0xbea2be8e,0x3d493dc8,0xbeffbefb,
0x3efb3f00,0xbdc80000,0xbdc80000,0xbefbbf00,0x3ed53eed,0xbe8ebe44,0xbe8ebe44,0xbed5beed,0x3e8e3eb5,0xbed5beb5,0xbed5beb5,0xbe8ebeb5,0x3dc83e44,0xbefbbeed,0xbefbbeed,0xbdc8be44,
0x3ef53f00,0xbe150000,0xbee2beb5,0xbe71beb5,0x3ea23ed5,0xbec6be8e,0xbeffbefb,0x3d49bdc8,0x3d493e44,0xbeffbeed,0xbec6beed,0x3ea23e44,0xbe71bdc8,0xbee2befb,0xbe15be8e,0x3ef53ed5,
0x3eed3f00,0xbe440000,0xbeedbf00,0x3e440000,0x3e443eb5,0xbeedbeb5,0xbe44beb5,0x3eed3eb5,0xbe440000,0xbeedbf00,0x3e440000,0x3eed3f00,0xbeedbeb5,0xbe44beb5,0x3eed3eb5,0x3e443eb5,
0x3ee23f00,0xbe710000,0xbe15beb5,0x3ef53eb5,0x3d493e8e,0xbeffbed5,0x3ea23dc8,0x3ec63efb,0xbec6be44,0xbea2beed,0x3eff3eed,0xbd493e44,0xbef5befb,0x3e15bdc8,0x3e713ed5,0xbee2be8e,
0x3ed53f00,0xbe8e0000,0x3e8e0000,0x3ed53f00,0xbdc83e44,0xbefbbeed,0x3efb3eed,0xbdc83e44,0xbefbbeb5,0xbdc8beb5,0x3dc83eb5,0xbefbbeb5,0xbe8ebeed,0x3ed53e44,0xbed5be44,0xbe8ebeed,
0x3ec63f00,0xbea20000,0x3eff3eb5,0x3d493eb5,0xbe713dc8,0xbee2befb,0x3e153ed5,0xbef5be8e,0xbef5beed,0x3e15be44,0xbee2be44,0xbe71beed,0x3d49be8e,0x3eff3ed5,0xbea2befb,0x3ec63dc8,
0x3f00,0xbf000000,0x3f00,0xbf000000,0xbf00,0x3f000000,0xbf00,0x3f000000,0x3f00,0xbf000000,0x3f00,0xbf000000,0xbf00,0x3f000000,0xbf00,0x3f000000,
0xbd493f00,0xbeff0000,0xbec63eb5,0xbea2beb5,0x3e15befb,0x3ef53dc8,0x3ee2be8e,0x3e713ed5,0xbe713eed,0xbee2be44,0xbef53e44,0xbe15beed,0x3ea2bed5,0x3ec63e8e,0x3effbdc8,0x3d493efb,
0xbdc83f00,0xbefb0000,0xbefb0000,0x3dc8bf00,0x3e8ebeed,0x3ed53e44,0x3ed53e44,0xbe8e3eed,0xbed53eb5,0xbe8ebeb5,0xbe8ebeb5,0x3ed5beb5,0x3efbbe44,0x3dc83eed,0x3dc83eed,0xbefb3e44,
0xbe153f00,0xbef50000,0xbe71beb5,0x3ee2beb5,0x3ec6bed5,0x3ea23e8e,0xbd493efb,0xbeff3dc8,0xbeff3e44,0xbd49beed,0x3ea2beed,0x3ec63e44,0x3ee23dc8,0xbe713efb,0xbef53e8e,0xbe15bed5,
0xbe443f00,0xbeed0000,0x3e44bf00,0x3eed0000,0x3eedbeb5,0x3e443eb5,0xbeed3eb5,0xbe44beb5,0xbeed0000,0x3e44bf00,0x3eed0000,0xbe443f00,0x3e443eb5,0xbeed3eb5,0xbe44beb5,0x3eedbeb5,
0xbe713f00,0xbee20000,0x3ef5beb5,0x3e153eb5,0x3effbe8e,0x3d493ed5,0xbec6bdc8,0x3ea2befb,0xbea2be44,0x3ec6beed,0xbd493eed,0xbeff3e44,0xbe153efb,0xbef53dc8,0x3ee2bed5,0x3e713e8e,
0xbe8e3f00,0xbed50000,0x3ed50000,0xbe8e3f00,0x3efbbe44,0xbdc83eed,0x3dc8beed,0x3efbbe44,0xbdc8beb5,0x3efbbeb5,0xbefb3eb5,0xbdc8beb5,0xbed53eed,0xbe8ebe44,0x3e8e3e44,0xbed53eed,
0xbea23f00,0xbec60000,0x3d493eb5,0xbeff3eb5,0x3ee2bdc8,0xbe713efb,0x3ef5bed5,0x3e153e8e,0x3e15beed,0x3ef5be44,0xbe71be44,0x3ee2beed,0xbeff3e8e,0x3d49bed5,0xbec63efb,0xbea2bdc8,
0x3eb53f00,0xbeb50000,0x3eb53f00,0xbeb50000,0xbeb50000,0xbeb5bf00,0xbeb50000,0xbeb5bf00,0xbeb5bf00,0x3eb50000,0xbeb5bf00,0x3eb50000,0x3eb50000,0x3eb53f00,0x3eb50000,0x3eb53f00,
0xbeff3f00,0x3d490000,0xbea23eb5,0x3ec6beb5,0xbef53efb,0x3e15bdc8,0xbe713e8e,0x3ee2bed5,0xbee23eed,0x3e71be44,0xbe153e44,0x3ef5beed,0xbec63ed5,0x3ea2be8e,0xbd493dc8,0x3effbefb,
0xbefb3f00,0x3dc80000,0x3dc80000,0x3efbbf00,0xbed53eed,0x3e8ebe44,0x3e8ebe44,0x3ed5beed,0xbe8e3eb5,0x3ed5beb5,0x3ed5beb5,0x3e8ebeb5,0xbdc83e44,0x3efbbeed,0x3efbbeed,0x3dc8be44,
0xbef53f00,0x3e150000,0x3ee2beb5,0x3e71beb5,0xbea23ed5,0x3ec6be8e,0x3effbefb,0xbd49bdc8,0xbd493e44,0x3effbeed,0x3ec6beed,0xbea23e44,0x3e71bdc8,0x3ee2befb,0x3e15be8e,0xbef53ed5,
0xbeed3f00,0x3e440000,0x3eedbf00,0xbe440000,0xbe443eb5,0x3eedbeb5,0x3e44beb5,0xbeed3eb5,0x3e440000,0x3eedbf00,0xbe440000,0xbeed3f00,0x3eedbeb5,0x3e44beb5,0xbeed3eb5,0xbe443eb5,
0xbee23f00,0x3e710000,0x3e15beb5,0xbef53eb5,0xbd493e8e,0x3effbed5,0xbea23dc8,0xbec63efb,0x3ec6be44,0x3ea2beed,0xbeff3eed,0x3d493e44,0x3ef5befb,0xbe15bdc8,0xbe713ed5,0x3ee2be8e,
0xbed53f00,0x3e8e0000,0xbe8e0000,0xbed53f00,0x3dc83e44,0x3efbbeed,0xbefb3eed,0x3dc83e44,0x3efbbeb5,0x3dc8beb5,0xbdc83eb5,0x3efbbeb5,0x3e8ebeed,0xbed53e44,0x3ed5be44,0x3e8ebeed,
0xbec63f00,0x3ea20000,0xbeff3eb5,0xbd493eb5,0x3e713dc8,0x3ee2befb,0xbe153ed5,0x3ef5be8e,0x3ef5beed,0xbe15be44,0x3ee2be44,0x3e71beed,0xbd49be8e,0xbeff3ed5,0x3ea2befb,0xbec63dc8,
0xbeb53f00,0xbeb50000,0xbeb53f00,0xbeb50000,0x3eb50000,0xbeb53f00,0x3eb50000,0xbeb53f00,0x3eb5bf00,0x3eb50000,0x3eb5bf00,0x3eb50000,0xbeb50000,0x3eb5bf00,0xbeb50000,0x3eb5bf00,
0x3d493f00,0x3eff0000,0x3ec63eb5,0x3ea2beb5,0xbe15befb,0xbef53dc8,0xbee2be8e,0xbe713ed5,0x3e713eed,0x3ee2be44,0x3ef53e44,0x3e15beed,0xbea2bed5,0xbec63e8e,0xbeffbdc8,0xbd493efb,
0x3dc83f00,0x3efb0000,0x3efb0000,0xbdc8bf00,0xbe8ebeed,0xbed53e44,0xbed53e44,0x3e8e3eed,0x3ed53eb5,0x3e8ebeb5,0x3e8ebeb5,0xbed5beb5,0xbefbbe44,0xbdc83eed,0xbdc83eed,0x3efb3e44,
0x3e153f00,0x3ef50000,0x3e71beb5,0xbee2beb5,0xbec6bed5,0xbea23e8e,0x3d493efb,0x3eff3dc8,0x3eff3e44,0x3d49beed,0xbea2beed,0xbec63e44,0xbee23dc8,0x3e713efb,0x3ef53e8e,0x3e15bed5,
0x3e443f00,0x3eed0000,0xbe44bf00,0xbeed0000,0xbeedbeb5,0xbe443eb5,0x3eed3eb5,0x3e44beb5,0x3eed0000,0xbe44bf00,0xbeed0000,0x3e443f00,0xbe443eb5,0x3eed3eb5,0x3e44beb5,0xbeedbeb5,
0x3e713f00,0x3ee20000,0xbef5beb5,0xbe153eb5,0xbeffbe8e,0xbd493ed5,0x3ec6bdc8,0xbea2befb,0x3ea2be44,0xbec6beed,0x3d493eed,0x3eff3e44,0x3e153efb,0x3ef53dc8,0xbee2bed5,0xbe713e8e,
0x3e8e3f00,0x3ed50000,0xbed50000,0x3e8e3f00,0xbefbbe44,0x3dc83eed,0xbdc8beed,0xbefbbe44,0x3dc8beb5,0xbefbbeb5,0x3efb3eb5,0x3dc8beb5,0x3ed53eed,0x3e8ebe44,0xbe8e3e44,0x3ed53eed,
0x3ea23f00,0x3ec60000,0xbd493eb5,0x3eff3eb5,0xbee2bdc8,0x3e713efb,0xbef5bed5,0xbe153e8e,0xbe15beed,0xbef5be44,0x3e71be44,0xbee2beed,0x3eff3e8e,0xbd49bed5,0x3ec63efb,0x3ea2bdc8,
0x3f003f00,0xbf003f00,0x3f003f00,0xbf003f00,0x3f003f00,0xbf003f00,0x3f003f00,0xbf003f00,0x3f003f00,0xbf003f00,0x3f003f00,0xbf003f00,0x3f003f00,0xbf003f00,0x3f003f00,0xbf003f00,
0xbd490000,0xbeffbf00,0xbec6beb5,0xbea2beb5,0xbe15bdc8,0xbef5befb,0xbee2bed5,0xbe71be8e,0xbe71be44,0xbee2beed,0xbef5beed,0xbe15be44,0xbea2be8e,0xbec6bed5,0xbeffbefb,0xbd49bdc8,
0xbefbbf00,0x3dc80000,0x3dc80000,0x3efb3f00,0xbed5beed,0x3e8e3e44,0x3e8e3e44,0x3ed53eed,0xbe8ebeb5,0x3ed53eb5,0x3ed53eb5,0x3e8e3eb5,0xbdc8be44,0x3efb3eed,0x3efb3eed,0x3dc83e44,
0x3e150000,0x3ef53f00,0x3e713eb5,0xbee2beb5,0x3ec63e8e,0x3ea23ed5,0xbd493dc8,0xbeffbefb,0x3eff3eed,0x3d493e44,0xbea2be44,0xbec6beed,0x3ee23efb,0xbe71bdc8,0xbef5bed5,0xbe15be8e,
0x3eed3f00,0xbe440000,0xbeedbf00,0x3e440000,0x3e443eb5,0xbeedbeb5,0xbe44beb5,0x3eed3eb5,0xbe440000,0xbeedbf00,0x3e440000,0x3eed3f00,0xbeedbeb5,0xbe44beb5,0x3eed3eb5,0x3e443eb5,
0xbe710000,0xbee2bf00,0x3ef53eb5,0x3e153eb5,0xbeffbed5,0xbd49be8e,0x3ec63efb,0xbea2bdc8,0xbea2beed,0x3ec63e44,0xbd493e44,0xbeffbeed,0x3e15bdc8,0x3ef53efb,0xbee2be8e,0xbe71bed5,
0xbed5bf00,0x3e8e0000,0xbe8e0000,0xbed5bf00,0x3dc8be44,0x3efb3eed,0xbefbbeed,0x3dc8be44,0x3efb3eb5,0x3dc83eb5,0xbdc8beb5,0x3efb3eb5,0x3e8e3eed,0xbed5be44,0x3ed53e44,0x3e8e3eed,
0x3ea20000,0x3ec63f00,0xbd49beb5,0x3eff3eb5,0x3ee23efb,0xbe713dc8,0x3ef53e8e,0x3e153ed5,0xbe153e44,0xbef5beed,0x3e713eed,0xbee2be44,0xbeffbed5,0x3d49be8e,0xbec6bdc8,0xbea2befb,
0x3f00,0xbf000000,0x3f00,0xbf000000,0xbf00,0x3f000000,0xbf00,0x3f000000,0x3f00,0xbf000000,0x3f00,0xbf000000,0xbf00,0x3f000000,0xbf00,0x3f000000,
0xbeff0000,0x3d49bf00,0xbea2beb5,0x3ec6beb5,0x3ef53dc8,0xbe153efb,0x3e713ed5,0xbee23e8e,0xbee2be44,0x3e71beed,0xbe15beed,0x3ef5be44,0x3ec63e8e,0xbea23ed5,0x3d493efb,0xbeff3dc8,
0x3dc8bf00,0x3efb0000,0x3efb0000,0xbdc83f00,0xbe8e3eed,0xbed5be44,0xbed5be44,0x3e8ebeed,0x3ed5beb5,0x3e8e3eb5,0x3e8e3eb5,0xbed53eb5,0xbefb3e44,0xbdc8beed,0xbdc8beed,0x3efbbe44,
0x3ef50000,0xbe153f00,0xbee23eb5,0xbe71beb5,0xbea2be8e,0x3ec6bed5,0x3effbdc8,0xbd493efb,0x3d493eed,0xbeff3e44,0xbec6be44,0x3ea2beed,0x3e71befb,0x3ee23dc8,0x3e153ed5,0xbef53e8e,
0xbe443f00,0xbeed0000,0x3e44bf00,0x3eed0000,0x3eedbeb5,0x3e443eb5,0xbeed3eb5,0xbe44beb5,0xbeed0000,0x3e44bf00,0x3eed0000,0xbe443f00,0x3e443eb5,0xbeed3eb5,0xbe44beb5,0x3eedbeb5,
0xbee20000,0x3e71bf00,0x3e153eb5,0xbef53eb5,0x3d493ed5,0xbeff3e8e,0x3ea2befb,0x3ec63dc8,0x3ec6beed,0x3ea23e44,0xbeff3e44,0x3d49beed,0xbef53dc8,0x3e15befb,0x3e713e8e,0xbee23ed5,
0x3e8ebf00,0x3ed50000,0xbed50000,0x3e8ebf00,0xbefb3e44,0x3dc8beed,0xbdc83eed,0xbefb3e44,0x3dc83eb5,0xbefb3eb5,0x3efbbeb5,0x3dc83eb5,0x3ed5beed,0x3e8e3e44,0xbe8ebe44,0x3ed5beed,
0x3ec60000,0xbea23f00,0x3effbeb5,0x3d493eb5,0x3e71befb,0x3ee2bdc8,0xbe15be8e,0x3ef5bed5,0xbef53e44,0x3e15beed,0xbee23eed,0xbe71be44,0xbd493ed5,0xbeff3e8e,0x3ea23dc8,0xbec63efb,
0x3eb53f00,0xbeb50000,0x3eb53f00,0xbeb50000,0xbeb50000,0xbeb5bf00,0xbeb50000,0xbeb5bf00,0xbeb5bf00,0x3eb50000,0xbeb5bf00,0x3eb50000,0x3eb50000,0x3eb53f00,0x3eb50000,0x3eb53f00,
0x3d490000,0x3effbf00,0x3ec6beb5,0x3ea2beb5,0x3e15bdc8,0x3ef5befb,0x3ee2bed5,0x3e71be8e,0x3e71be44,0x3ee2beed,0x3ef5beed,0x3e15be44,0x3ea2be8e,0x3ec6bed5,0x3effbefb,0x3d49bdc8,
0x3efbbf00,0xbdc80000,0xbdc80000,0xbefb3f00,0x3ed5beed,0xbe8e3e44,0xbe8e3e44,0xbed53eed,0x3e8ebeb5,0xbed53eb5,0xbed53eb5,0xbe8e3eb5,0x3dc8be44,0xbefb3eed,0xbefb3eed,0xbdc83e44,
0xbe150000,0xbef53f00,0xbe713eb5,0x3ee2beb5,0xbec63e8e,0xbea23ed5,0x3d493dc8,0x3effbefb,0xbeff3eed,0xbd493e44,0x3ea2be44,0x3ec6beed,0xbee23efb,0x3e71bdc8,0x3ef5bed5,0x3e15be8e,
0xbeed3f00,0x3e440000,0x3eedbf00,0xbe440000,0xbe443eb5,0x3eedbeb5,0x3e44beb5,0xbeed3eb5,0x3e440000,0x3eedbf00,0xbe440000,0xbeed3f00,0x3eedbeb5,0x3e44beb5,0xbeed3eb5,0xbe443eb5,
0x3e710000,0x3ee2bf00,0xbef53eb5,0xbe153eb5,0x3effbed5,0x3d49be8e,0xbec63efb,0x3ea2bdc8,0x3ea2beed,0xbec63e44,0x3d493e44,0x3effbeed,0xbe15bdc8,0xbef53efb,0x3ee2be8e,0x3e71bed5,
0x3ed5bf00,0xbe8e0000,0x3e8e0000,0x3ed5bf00,0xbdc8be44,0xbefb3eed,0x3efbbeed,0xbdc8be44,0xbefb3eb5,0xbdc83eb5,0x3dc8beb5,0xbefb3eb5,0xbe8e3eed,0x3ed5be44,0xbed53e44,0xbe8e3eed,
0xbea20000,0xbec63f00,0x3d49beb5,0xbeff3eb5,0xbee23efb,0x3e713dc8,0xbef53e8e,0xbe153ed5,0x3e153e44,0x3ef5beed,0xbe713eed,0x3ee2be44,0x3effbed5,0xbd49be8e,0x3ec6bdc8,0x3ea2befb,
0xbeb53f00,0xbeb50000,0xbeb53f00,0xbeb50000,0x3eb50000,0xbeb53f00,0x3eb50000,0xbeb53f00,0x3eb5bf00,0x3eb50000,0x3eb5bf00,0x3eb50000,0xbeb50000,0x3eb5bf00,0xbeb50000,0x3eb5bf00,
0x3eff0000,0xbd49bf00,0x3ea2beb5,0xbec6beb5,0xbef53dc8,0x3e153efb,0xbe713ed5,0x3ee23e8e,0x3ee2be44,0xbe71beed,0x3e15beed,0xbef5be44,0xbec63e8e,0x3ea23ed5,0xbd493efb,0x3eff3dc8,
0xbdc8bf00,0xbefb0000,0xbefb0000,0x3dc83f00,0x3e8e3eed,0x3ed5be44,0x3ed5be44,0xbe8ebeed,0xbed5beb5,0xbe8e3eb5,0xbe8e3eb5,0x3ed53eb5,0x3efb3e44,0x3dc8beed,0x3dc8beed,0xbefbbe44,
0xbef50000,0x3e153f00,0x3ee23eb5,0x3e71beb5,0x3ea2be8e,0xbec6bed5,0xbeffbdc8,0x3d493efb,0xbd493eed,0x3eff3e44,0x3ec6be44,0xbea2beed,0xbe71befb,0xbee23dc8,0xbe153ed5,0x3ef53e8e,
0x3e443f00,0x3eed0000,0xbe44bf00,0xbeed0000,0xbeedbeb5,0xbe443eb5,0x3eed3eb5,0x3e44beb5,0x3eed0000,0xbe44bf00,0xbeed0000,0x3e443f00,0xbe443eb5,0x3eed3eb5,0x3e44beb5,0xbeedbeb5,
0x3ee20000,0xbe71bf00,0xbe153eb5,0x3ef53eb5,0xbd493ed5,0x3eff3e8e,0xbea2befb,0xbec63dc8,0xbec6beed,0xbea23e44,0x3eff3e44,0xbd49beed,0x3ef53dc8,0xbe15befb,0xbe713e8e,0x3ee23ed5,
0xbe8ebf00,0xbed50000,0x3ed50000,0xbe8ebf00,0x3efb3e44,0xbdc8beed,0x3dc83eed,0x3efb3e44,0xbdc83eb5,0x3efb3eb5,0xbefbbeb5,0xbdc83eb5,0xbed5beed,0xbe8e3e44,0x3e8ebe44,0xbed5beed,
0xbec60000,0x3ea23f00,0xbeffbeb5,0xbd493eb5,0xbe71befb,0xbee2bdc8,0x3e15be8e,0xbef5bed5,0x3ef53e44,0xbe15beed,0x3ee23eed,0x3e71be44,0x3d493ed5,0x3eff3e8e,0xbea23dc8,0x3ec63efb,
0x3f003f00,0xbf003f00,0x3f003f00,0xbf003f00,0x3f003f00,0xbf003f00,0x3f003f00,0xbf003f00,0x3f003f00,0xbf003f00,0x3f003f00,0xbf003f00,0x3f003f00,0xbf003f00,0x3f003f00,0xbf003f00,
0xbeffbf00,0x3d490000,0xbea2beb5,0x3ec63eb5,0xbef5befb,0x3e153dc8,0xbe71be8e,0x3ee23ed5,0xbee2beed,0x3e713e44,0xbe15be44,0x3ef53eed,0xbec6bed5,0x3ea23e8e,0xbd49bdc8,0x3eff3efb,
0x3efb3f00,0xbdc80000,0xbdc80000,0xbefbbf00,0x3ed53eed,0xbe8ebe44,0xbe8ebe44,0xbed5beed,0x3e8e3eb5,0xbed5beb5,0xbed5beb5,0xbe8ebeb5,0x3dc83e44,0xbefbbeed,0xbefbbeed,0xbdc8be44,
0xbef5bf00,0x3e150000,0x3ee23eb5,0x3e713eb5,0xbea2bed5,0x3ec63e8e,0x3eff3efb,0xbd493dc8,0xbd49be44,0x3eff3eed,0x3ec63eed,0xbea2be44,0x3e713dc8,0x3ee23efb,0x3e153e8e,0xbef5bed5,
0x3eed3f00,0xbe440000,0xbeedbf00,0x3e440000,0x3e443eb5,0xbeedbeb5,0xbe44beb5,0x3eed3eb5,0xbe440000,0xbeedbf00,0x3e440000,0x3eed3f00,0xbeedbeb5,0xbe44beb5,0x3eed3eb5,0x3e443eb5,
0xbee2bf00,0x3e710000,0x3e153eb5,0xbef5beb5,0xbd49be8e,0x3eff3ed5,0xbea2bdc8,0xbec6befb,0x3ec63e44,0x3ea23eed,0xbeffbeed,0x3d49be44,0x3ef53efb,0xbe153dc8,0xbe71bed5,0x3ee23e8e,
0x3ed53f00,0xbe8e0000,0x3e8e0000,0x3ed53f00,0xbdc83e44,0xbefbbeed,0x3efb3eed,0xbdc83e44,0xbefbbeb5,0xbdc8beb5,0x3dc83eb5,0xbefbbeb5,0xbe8ebeed,0x3ed53e44,0xbed5be44,0xbe8ebeed,
0xbec6bf00,0x3ea20000,0xbeffbeb5,0xbd49beb5,0x3e71bdc8,0x3ee23efb,0xbe15bed5,0x3ef53e8e,0x3ef53eed,0xbe153e44,0x3ee23e44,0x3e713eed,0xbd493e8e,0xbeffbed5,0x3ea23efb,0xbec6bdc8,
0x3f00,0xbf000000,0x3f00,0xbf000000,0xbf00,0x3f000000,0xbf00,0x3f000000,0x3f00,0xbf000000,0x3f00,0xbf000000,0xbf00,0x3f000000,0xbf00,0x3f000000,
0x3d49bf00,0x3eff0000,0x3ec6beb5,0x3ea23eb5,0xbe153efb,0xbef5bdc8,0xbee23e8e,0xbe71bed5,0x3e71beed,0x3ee23e44,0x3ef5be44,0x3e153eed,0xbea23ed5,0xbec6be8e,0xbeff3dc8,0xbd49befb,
0xbdc83f00,0xbefb0000,0xbefb0000,0x3dc8bf00,0x3e8ebeed,0x3ed53e44,0x3ed53e44,0xbe8e3eed,0xbed53eb5,0xbe8ebeb5,0xbe8ebeb5,0x3ed5beb5,0x3efbbe44,0x3dc83eed,0x3dc83eed,0xbefb3e44,
0x3e15bf00,0x3ef50000,0x3e713eb5,0xbee23eb5,0xbec63ed5,0xbea2be8e,0x3d49befb,0x3effbdc8,0x3effbe44,0x3d493eed,0xbea23eed,0xbec6be44,0xbee2bdc8,0x3e71befb,0x3ef5be8e,0x3e153ed5,
0xbe443f00,0xbeed0000,0x3e44bf00,0x3eed0000,0x3eedbeb5,0x3e443eb5,0xbeed3eb5,0xbe44beb5,0xbeed0000,0x3e44bf00,0x3eed0000,0xbe443f00,0x3e443eb5,0xbeed3eb5,0xbe44beb5,0x3eedbeb5,
0x3e71bf00,0x3ee20000,0xbef53eb5,0xbe15beb5,0xbeff3e8e,0xbd49bed5,0x3ec63dc8,0xbea23efb,0x3ea23e44,0xbec63eed,0x3d49beed,0x3effbe44,0x3e15befb,0x3ef5bdc8,0xbee23ed5,0xbe71be8e,
0xbe8e3f00,0xbed50000,0x3ed50000,0xbe8e3f00,0x3efbbe44,0xbdc83eed,0x3dc8beed,0x3efbbe44,0xbdc8beb5,0x3efbbeb5,0xbefb3eb5,0xbdc8beb5,0xbed53eed,0xbe8ebe44,0x3e8e3e44,0xbed53eed,
0x3ea2bf00,0x3ec60000,0xbd49beb5,0x3effbeb5,0xbee23dc8,0x3e71befb,0xbef53ed5,0xbe15be8e,0xbe153eed,0xbef53e44,0x3e713e44,0xbee23eed,0x3effbe8e,0xbd493ed5,0x3ec6befb,0x3ea23dc8,
0x3eb53f00,0xbeb50000,0x3eb53f00,0xbeb50000,0xbeb50000,0xbeb5bf00,0xbeb50000,0xbeb5bf00,0xbeb5bf00,0x3eb50000,0xbeb5bf00,0x3eb50000,0x3eb50000,0x3eb53f00,0x3eb50000,0x3eb53f00,
0x3effbf00,0xbd490000,0x3ea2beb5,0xbec63eb5,0x3ef5befb,0xbe153dc8,0x3e71be8e,0xbee23ed5,0x3ee2beed,0xbe713e44,0x3e15be44,0xbef53eed,0x3ec6bed5,0xbea23e8e,0x3d49bdc8,0xbeff3efb,
0xbefb3f00,0x3dc80000,0x3dc80000,0x3efbbf00,0xbed53eed,0x3e8ebe44,0x3e8ebe44,0x3ed5beed,0xbe8e3eb5,0x3ed5beb5,0x3ed5beb5,0x3e8ebeb5,0xbdc83e44,0x3efbbeed,0x3efbbeed,0x3dc8be44,
0x3ef5bf00,0xbe150000,0xbee23eb5,0xbe713eb5,0x3ea2bed5,0xbec63e8e,0xbeff3efb,0x3d493dc8,0x3d49be44,0xbeff3eed,0xbec63eed,0x3ea2be44,0xbe713dc8,0xbee23efb,0xbe153e8e,0x3ef5bed5,
0xbeed3f00,0x3e440000,0x3eedbf00,0xbe440000,0xbe443eb5,0x3eedbeb5,0x3e44beb5,0xbeed3eb5,0x3e440000,0x3eedbf00,0xbe440000,0xbeed3f00,0x3eedbeb5,0x3e44beb5,0xbeed3eb5,0xbe443eb5,
0x3ee2bf00,0xbe710000,0xbe153eb5,0x3ef5beb5,0x3d49be8e,0xbeff3ed5,0x3ea2bdc8,0x3ec6befb,0xbec63e44,0xbea23eed,0x3effbeed,0xbd49be44,0xbef53efb,0x3e153dc8,0x3e71bed5,0xbee23e8e,
0xbed53f00,0x3e8e0000,0xbe8e0000,0xbed53f00,0x3dc83e44,0x3efbbeed,0xbefb3eed,0x3dc83e44,0x3efbbeb5,0x3dc8beb5,0xbdc83eb5,0x3efbbeb5,0x3e8ebeed,0xbed53e44,0x3ed5be44,0x3e8ebeed,
0x3ec6bf00,0xbea20000,0x3effbeb5,0x3d49beb5,0xbe71bdc8,0xbee23efb,0x3e15bed5,0xbef53e8e,0xbef53eed,0x3e153e44,0xbee23e44,0xbe713eed,0x3d493e8e,0x3effbed5,0xbea23efb,0x3ec6bdc8,
0xbeb53f00,0xbeb50000,0xbeb53f00,0xbeb50000,0x3eb50000,0xbeb53f00,0x3eb50000,0xbeb53f00,0x3eb5bf00,0x3eb50000,0x3eb5bf00,0x3eb50000,0xbeb50000,0x3eb5bf00,0xbeb50000,0x3eb5bf00,
0xbd49bf00,0xbeff0000,0xbec6beb5,0xbea23eb5,0x3e153efb,0x3ef5bdc8,0x3ee23e8e,0x3e71bed5,0xbe71beed,0xbee23e44,0xbef5be44,0xbe153eed,0x3ea23ed5,0x3ec6be8e,0x3eff3dc8,0x3d49befb,
0x3dc83f00,0x3efb0000,0x3efb0000,0xbdc8bf00,0xbe8ebeed,0xbed53e44,0xbed53e44,0x3e8e3eed,0x3ed53eb5,0x3e8ebeb5,0x3e8ebeb5,0xbed5beb5,0xbefbbe44,0xbdc83eed,0xbdc83eed,0x3efb3e44,
0xbe15bf00,0xbef50000,0xbe713eb5,0x3ee23eb5,0x3ec63ed5,0x3ea2be8e,0xbd49befb,0xbeffbdc8,0xbeffbe44,0xbd493eed,0x3ea23eed,0x3ec6be44,0x3ee2bdc8,0xbe71befb,0xbef5be8e,0xbe153ed5,
0x3e443f00,0x3eed0000,0xbe44bf00,0xbeed0000,0xbeedbeb5,0xbe443eb5,0x3eed3eb5,0x3e44beb5,0x3eed0000,0xbe44bf00,0xbeed0000,0x3e443f00,0xbe443eb5,0x3eed3eb5,0x3e44beb5,0xbeedbeb5,
0xbe71bf00,0xbee20000,0x3ef53eb5,0x3e15beb5,0x3eff3e8e,0x3d49bed5,0xbec63dc8,0x3ea23efb,0xbea23e44,0x3ec63eed,0xbd49beed,0xbeffbe44,0xbe15befb,0xbef5bdc8,0x3ee23ed5,0x3e71be8e,
0x3e8e3f00,0x3ed50000,0xbed50000,0x3e8e3f00,0xbefbbe44,0x3dc83eed,0xbdc8beed,0xbefbbe44,0x3dc8beb5,0xbefbbeb5,0x3efb3eb5,0x3dc8beb5,0x3ed53eed,0x3e8ebe44,0xbe8e3e44,0x3ed53eed,
0xbea2bf00,0xbec60000,0x3d49beb5,0xbeffbeb5,0x3ee23dc8,0xbe71befb,0x3ef53ed5,0x3e15be8e,0x3e153eed,0x3ef53e44,0xbe713e44,0x3ee23eed,0xbeffbe8e,0x3d493ed5,0xbec6befb,0xbea23dc8,
0x3f003f00,0xbf003f00,0x3f003f00,0xbf003f00,0x3f003f00,0xbf003f00,0x3f003f00,0xbf003f00,0x3f003f00,0xbf003f00,0x3f003f00,0xbf003f00,0x3f003f00,0xbf003f00,0x3f003f00,0xbf003f00,
0x3d490000,0x3eff3f00,0x3ec63eb5,0x3ea23eb5,0x3e153dc8,0x3ef53efb,0x3ee23ed5,0x3e713e8e,0x3e713e44,0x3ee23eed,0x3ef53eed,0x3e153e44,0x3ea23e8e,0x3ec63ed5,0x3eff3efb,0x3d493dc8,
0xbefbbf00,0x3dc80000,0x3dc80000,0x3efb3f00,0xbed5beed,0x3e8e3e44,0x3e8e3e44,0x3ed53eed,0xbe8ebeb5,0x3ed53eb5,0x3ed53eb5,0x3e8e3eb5,0xbdc8be44,0x3efb3eed,0x3efb3eed,0x3dc83e44,
0xbe150000,0xbef5bf00,0xbe71beb5,0x3ee23eb5,0xbec6be8e,0xbea2bed5,0x3d49bdc8,0x3eff3efb,0xbeffbeed,0xbd49be44,0x3ea23e44,0x3ec63eed,0xbee2befb,0x3e713dc8,0x3ef53ed5,0x3e153e8e,
0x3eed3f00,0xbe440000,0xbeedbf00,0x3e440000,0x3e443eb5,0xbeedbeb5,0xbe44beb5,0x3eed3eb5,0xbe440000,0xbeedbf00,0x3e440000,0x3eed3f00,0xbeedbeb5,0xbe44beb5,0x3eed3eb5,0x3e443eb5,
0x3e710000,0x3ee23f00,0xbef5beb5,0xbe15beb5,0x3eff3ed5,0x3d493e8e,0xbec6befb,0x3ea23dc8,0x3ea23eed,0xbec6be44,0x3d49be44,0x3eff3eed,0xbe153dc8,0xbef5befb,0x3ee23e8e,0x3e713ed5,
0xbed5bf00,0x3e8e0000,0xbe8e0000,0xbed5bf00,0x3dc8be44,0x3efb3eed,0xbefbbeed,0x3dc8be44,0x3efb3eb5,0x3dc83eb5,0xbdc8beb5,0x3efb3eb5,0x3e8e3eed,0xbed5be44,0x3ed53e44,0x3e8e3eed,
0xbea20000,0xbec6bf00,0x3d493eb5,0xbeffbeb5,0xbee2befb,0x3e71bdc8,0xbef5be8e,0xbe15bed5,0x3e15be44,0x3ef53eed,0xbe71beed,0x3ee23e44,0x3eff3ed5,0xbd493e8e,0x3ec63dc8,0x3ea23efb,
0x3f00,0xbf000000,0x3f00,0xbf000000,0xbf00,0x3f000000,0xbf00,0x3f000000,0x3f00,0xbf000000,0x3f00,0xbf000000,0xbf00,0x3f000000,0xbf00,0x3f000000,
0x3eff0000,0xbd493f00,0x3ea23eb5,0xbec63eb5,0xbef5bdc8,0x3e15befb,0xbe71bed5,0x3ee2be8e,0x3ee23e44,0xbe713eed,0x3e153eed,0xbef53e44,0xbec6be8e,0x3ea2bed5,0xbd49befb,0x3effbdc8,
0x3dc8bf00,0x3efb0000,0x3efb0000,0xbdc83f00,0xbe8e3eed,0xbed5be44,0xbed5be44,0x3e8ebeed,0x3ed5beb5,0x3e8e3eb5,0x3e8e3eb5,0xbed53eb5,0xbefb3e44,0xbdc8beed,0xbdc8beed,0x3efbbe44,
0xbef50000,0x3e15bf00,0x3ee2beb5,0x3e713eb5,0x3ea23e8e,0xbec63ed5,0xbeff3dc8,0x3d49befb,0xbd49beed,0x3effbe44,0x3ec63e44,0xbea23eed,0xbe713efb,0xbee2bdc8,0xbe15bed5,0x3ef5be8e,
0xbe443f00,0xbeed0000,0x3e44bf00,0x3eed0000,0x3eedbeb5,0x3e443eb5,0xbeed3eb5,0xbe44beb5,0xbeed0000,0x3e44bf00,0x3eed0000,0xbe443f00,0x3e443eb5,0xbeed3eb5,0xbe44beb5,0x3eedbeb5,
0x3ee20000,0xbe713f00,0xbe15beb5,0x3ef5beb5,0xbd49bed5,0x3effbe8e,0xbea23efb,0xbec6bdc8,0xbec63eed,0xbea2be44,0x3effbe44,0xbd493eed,0x3ef5bdc8,0xbe153efb,0xbe71be8e,0x3ee2bed5,
0x3e8ebf00,0x3ed50000,0xbed50000,0x3e8ebf00,0xbefb3e44,0x3dc8beed,0xbdc83eed,0xbefb3e44,0x3dc83eb5,0xbefb3eb5,0x3efbbeb5,0x3dc83eb5,0x3ed5beed,0x3e8e3e44,0xbe8ebe44,0x3ed5beed,
0xbec60000,0x3ea2bf00,0xbeff3eb5,0xbd49beb5,0xbe713efb,0xbee23dc8,0x3e153e8e,0xbef53ed5,0x3ef5be44,0xbe153eed,0x3ee2beed,0x3e713e44,0x3d49bed5,0x3effbe8e,0xbea2bdc8,0x3ec6befb,
0x3eb53f00,0xbeb50000,0x3eb53f00,0xbeb50000,0xbeb50000,0xbeb5bf00,0xbeb50000,0xbeb5bf00,0xbeb5bf00,0x3eb50000,0xbeb5bf00,0x3eb50000,0x3eb50000,0x3eb53f00,0x3eb50000,0x3eb53f00,
0xbd490000,0xbeff3f00,0xbec63eb5,0xbea23eb5,0xbe153dc8,0xbef53efb,0xbee23ed5,0xbe713e8e,0xbe713e44,0xbee23eed,0xbef53eed,0xbe153e44,0xbea23e8e,0xbec63ed5,0xbeff3efb,0xbd493dc8,
0x3efbbf00,0xbdc80000,0xbdc80000,0xbefb3f00,0x3ed5beed,0xbe8e3e44,0xbe8e3e44,0xbed53eed,0x3e8ebeb5,0xbed53eb5,0xbed53eb5,0xbe8e3eb5,0x3dc8be44,0xbefb3eed,0xbefb3eed,0xbdc83e44,
0x3e150000,0x3ef5bf00,0x3e71beb5,0xbee23eb5,0x3ec6be8e,0x3ea2bed5,0xbd49bdc8,0xbeff3efb,0x3effbeed,0x3d49be44,0xbea23e44,0xbec63eed,0x3ee2befb,0xbe713dc8,0xbef53ed5,0xbe153e8e,
0xbeed3f00,0x3e440000,0x3eedbf00,0xbe440000,0xbe443eb5,0x3eedbeb5,0x3e44beb5,0xbeed3eb5,0x3e440000,0x3eedbf00,0xbe440000,0xbeed3f00,0x3eedbeb5,0x3e44beb5,0xbeed3eb5,0xbe443eb5,
0xbe710000,0xbee23f00,0x3ef5beb5,0x3e15beb5,0xbeff3ed5,0xbd493e8e,0x3ec6befb,0xbea23dc8,0xbea23eed,0x3ec6be44,0xbd49be44,0xbeff3eed,0x3e153dc8,0x3ef5befb,0xbee23e8e,0xbe713ed5,
0x3ed5bf00,0xbe8e0000,0x3e8e0000,0x3ed5bf00,0xbdc8be44,0xbefb3eed,0x3efbbeed,0xbdc8be44,0xbefb3eb5,0xbdc83eb5,0x3dc8beb5,0xbefb3eb5,0xbe8e3eed,0x3ed5be44,0xbed53e44,0xbe8e3eed,
0x3ea20000,0x3ec6bf00,0xbd493eb5,0x3effbeb5,0x3ee2befb,0xbe71bdc8,0x3ef5be8e,0x3e15bed5,0xbe15be44,0xbef53eed,0x3e71beed,0xbee23e44,0xbeff3ed5,0x3d493e8e,0xbec63dc8,0xbea23efb,
0xbeb53f00,0xbeb50000,0xbeb53f00,0xbeb50000,0x3eb50000,0xbeb53f00,0x3eb50000,0xbeb53f00,0x3eb5bf00,0x3eb50000,0x3eb5bf00,0x3eb50000,0xbeb50000,0x3eb5bf00,0xbeb50000,0x3eb5bf00,
0xbeff0000,0x3d493f00,0xbea23eb5,0x3ec63eb5,0x3ef5bdc8,0xbe15befb,0x3e71bed5,0xbee2be8e,0xbee23e44,0x3e713eed,0xbe153eed,0x3ef53e44,0x3ec6be8e,0xbea2bed5,0x3d49befb,0xbeffbdc8,
0xbdc8bf00,0xbefb0000,0xbefb0000,0x3dc83f00,0x3e8e3eed,0x3ed5be44,0x3ed5be44,0xbe8ebeed,0xbed5beb5,0xbe8e3eb5,0xbe8e3eb5,0x3ed53eb5,0x3efb3e44,0x3dc8beed,0x3dc8beed,0xbefbbe44,
0x3ef50000,0xbe15bf00,0xbee2beb5,0xbe713eb5,0xbea23e8e,0x3ec63ed5,0x3eff3dc8,0xbd49befb,0x3d49beed,0xbeffbe44,0xbec63e44,0x3ea23eed,0x3e713efb,0x3ee2bdc8,0x3e15bed5,0xbef5be8e,
0x3e443f00,0x3eed0000,0xbe44bf00,0xbeed0000,0xbeedbeb5,0xbe443eb5,0x3eed3eb5,0x3e44beb5,0x3eed0000,0xbe44bf00,0xbeed0000,0x3e443f00,0xbe443eb5,0x3eed3eb5,0x3e44beb5,0xbeedbeb5,
0xbee20000,0x3e713f00,0x3e15beb5,0xbef5beb5,0x3d49bed5,0xbeffbe8e,0x3ea23efb,0x3ec6bdc8,0x3ec63eed,0x3ea2be44,0xbeffbe44,0x3d493eed,0xbef5bdc8,0x3e153efb,0x3e71be8e,0xbee2bed5,
0xbe8ebf00,0xbed50000,0x3ed50000,0xbe8ebf00,0x3efb3e44,0xbdc8beed,0x3dc83eed,0x3efb3e44,0xbdc83eb5,0x3efb3eb5,0xbefbbeb5,0xbdc83eb5,0xbed5beed,0xbe8e3e44,0x3e8ebe44,0xbed5beed,
0x3ec60000,0xbea2bf00,0x3eff3eb5,0x3d49beb5,0x3e713efb,0x3ee23dc8,0xbe153e8e,0x3ef53ed5,0xbef5be44,0x3e153eed,0xbee2beed,0xbe713e44,0xbd49bed5,0xbeffbe8e,0x3ea2bdc8,0xbec6befb,
0x3f800000,0x0,0x3f800000,0x0,0x3f800000,0x0,0x3f800000,0x0,0x3f800000,0x0,0x3f800000,0x0,0x3f800000,0x0,0x3f800000,0x0,
0x3f800000,0x0,0x3f7fec43,0xbcc90ab0,0x3f7fb10f,0xbd48fb30,0x3f7f4e6d,0xbd96a905,0x3f7ec46d,0xbdc8bd36,0x3f7e1324,0xbdfab273,0x3f7d3aac,0xbe164083,0x3f7c3b28,0xbe2f10a2,
0x3f800000,0x0,0x3f7ffec4,0xbbc90f88,0x3f7ffb11,0xbc490e90,0x3f7ff4e6,0xbc96c9b6,0x3f7fec43,0xbcc90ab0,0x3f7fe129,0xbcfb49ba,0x3f7fd397,0xbd16c32c,0x3f7fc38f,0xbd2fe007,
0x3f800000,0x0,0x3f7fe129,0xbcfb49ba,0x3f7f84ab,0xbd7b2b74,0x3f7eea9d,0xbdbc3ac3,0x3f7e1324,0xbdfab273,0x3f7cfe73,0xbe1c76de,0x3f7baccd,0xbe3b6ecf,0x3f7a1e84,0xbe5a3997,
0x3f800000,0x0,0x3f7ffb11,0xbc490e90,0x3f7fec43,0xbcc90ab0,0x3f7fd397,0xbd16c32c,0x3f7fb10f,0xbd48fb30,0x3f7f84ab,0xbd7b2b74,0x3f7f4e6d,0xbd96a905,0x3f7f0e58,0xbdafb680,
0x3f800000,0x0,0x3f7fd397,0xbd16c32c,0x3f7f4e6d,0xbd96a905,0x3f7e70b0,0xbde1bc2e,0x3f7d3aac,0xbe164083,0x3f7baccd,0xbe3b6ecf,0x3f79c79d,0xbe605c13,0x3f778bc5,0xbe827dc0,
0x3f800000,0x0,0x3f7ff4e6,0xbc96c9b6,0x3f7fd397,0xbd16c32c,0x3f7f9c18,0xbd621469,0x3f7f4e6d,0xbd96a905,0x3f7eea9d,0xbdbc3ac3,0x3f7e70b0,0xbde1bc2e,0x3f7de0b1,0xbe039502,
0x3f800000,0x0,0x3f7fc38f,0xbd2fe007,0x3f7f0e58,0xbdafb680,0x3f7de0b1,0xbe039502,0x3f7c3b28,0xbe2f10a2,0x3f7a1e84,0xbe5a3997,0x3f778bc5,0xbe827dc0,0x3f748422,0xbe97a117,
0x3f800000,0x0,0x3f7fb10f,0xbd48fb30,0x3f7ec46d,0xbdc8bd36,0x3f7d3aac,0xbe164083,0x3f7b14be,0xbe47c5c2,0x3f7853f8,0xbe78cfcc,0x3f74fa0b,0xbe94a031,0x3f710908,0xbeac7cd4,
0x3f800000,0x0,0x3f7f4e6d,0xbd96a905,0x3f7d3aac,0xbe164083,0x3f79c79d,0xbe605c13,0x3f74fa0b,0xbe94a031,0x3f6ed89e,0xbeb8442a,0x3f676bd8,0xbedae880,0x3f5ebe05,0xbefc5d27,
0x3f800000,0x0,0x3f7f9c18,0xbd621469,0x3f7e70b0,0xbde1bc2e,0x3f7c7eb0,0xbe28defc,0x3f79c79d,0xbe605c13,0x3f764d97,0xbe8b9507,0x3f721352,0xbea68f12,0x3f6d1c1d,0xbec1071e,
0x3f800000,0x0,0x3f7f2f9d,0xbda3308c,0x3f7cbfc9,0xbe22abb6,0x3f78b47b,0xbe72b651,0x3f731447,0xbea09ae5,0x3f6be858,0xbec6d529,0x3f633c5a,0xbeebcbbb,0x3f591e6a,0xbf07a136,
0x3f800000,0x0,0x3f7f84ab,0xbd7b2b74,0x3f7e1324,0xbdfab273,0x3f7baccd,0xbe3b6ecf,0x3f7853f8,0xbe78cfcc,0x3f740bdd,0xbe9aa086,0x3f6ed89e,0xbeb8442a,0x3f68bf3c,0xbed53641,
0x3f800000,0x0,0x3f7f0e58,0xbdafb680,0x3f7c3b28,0xbe2f10a2,0x3f778bc5,0xbe827dc0,0x3f710908,0xbeac7cd4,0x3f68bf3c,0xbed53641,0x3f5ebe05,0xbefc5d27,0x3f531849,0xbf10d3cd,
0x3f800000,0x0,0x3f7f6ac7,0xbd8a200a,0x3f7dabcc,0xbe09cf86,0x3f7ac516,0xbe4dee60,0x3f76ba07,0xbe888e93,0x3f718f57,0xbea986c4,0x3f6b4b0c,0xbec9b953,0x3f63f473,0xbee900b7,
0x3f800000,0x0,0x3f7eea9d,0xbdbc3ac3,0x3f7baccd,0xbe3b6ecf,0x3f764d97,0xbe8b9507,0x3f6ed89e,0xbeb8442a,0x3f655e0b,0xbee363fa,0x3f59f26a,0xbf064b82,0x3f4cae79,0xbf19c200,
0x3f800000,0x0,0x3f7ec46d,0xbdc8bd36,0x3f7b14be,0xbe47c5c2,0x3f74fa0b,0xbe94a031,0x3f6c835e,0xbec3ef15,0x3f61c598,0xbef15aea,0x3f54db31,0xbf0e39da,0x3f45e403,0xbf226799,
0x3f800000,0x0,0x3f7e1324,0xbdfab273,0x3f7853f8,0xbe78cfcc,0x3f6ed89e,0xbeb8442a,0x3f61c598,0xbef15aea,0x3f514d3d,0xbf13682a,0x3f3daef9,0xbf2beb4a,0x3f273656,0xbf41d870,
0x3f800000,0x0,0x3f7e9bc9,0xbdd53db9,0x3f7a7302,0xbe541501,0x3f73913f,0xbe9d9e78,0x3f6a09a7,0xbecf7bca,0x3f5df6be,0xbeff17b2,0x3f4f7a1f,0xbf15f6d9,0x3f3ebc1b,0xbf2ac082,
0x3f800000,0x0,0x3f7de0b1,0xbe039502,0x3f778bc5,0xbe827dc0,0x3f6d1c1d,0xbec1071e,0x3f5ebe05,0xbefc5d27,0x3f4cae79,0xbf19c200,0x3f373a23,0xbf32c8c9,0x3f1ebc12,0xbf48d8b3,
0x3f800000,0x0,0x3f7e70b0,0xbde1bc2e,0x3f79c79d,0xbe605c13,0x3f721352,0xbea68f12,0x3f676bd8,0xbedae880,0x3f59f26a,0xbf064b82,0x3f49d112,0xbf1d7fd1,0x3f373a23,0xbf32c8c9,
0x3f800000,0x0,0x3f7dabcc,0xbe09cf86,0x3f76ba07,0xbe888e93,0x3f6b4b0c,0xbec9b953,0x3f5b941a,0xbf039c3d,0x3f47de65,0xbf1ff6cb,0x3f3085bb,0xbf396842,0x3f15f6d9,0xbf4f7a1f,
0x3f800000,0x0,0x3f7e4323,0xbdee3876,0x3f791298,0xbe6c9a7f,0x3f708066,0xbeaf713a,0x3f64aa59,0xbee63375,0x3f55b993,0xbf0cead0,0x3f43e200,0xbf24d225,0x3f2f61a5,0xbf3a7ca4,
0x3f800000,0x0,0x3f7d7474,0xbe1008b7,0x3f75dec6,0xbe8e9a22,0x3f696591,0xbed25a09,0x3f584853,0xbf08f59b,0x3f42de29,0xbf26050a,0x3f299415,0xbf3fc767,0x3f0cead0,0xbf55b993,
0x3f800000,0x0,0x3f7d3aac,0xbe164083,0x3f74fa0b,0xbe94a031,0x3f676bd8,0xbedae880,0x3f54db31,0xbf0e39da,0x3f3daef9,0xbf2beb4a,0x3f226799,0xbf45e403,0x3f039c3d,0xbf5b941a,
0x3f800000,0x0,0x3f7c3b28,0xbe2f10a2,0x3f710908,0xbeac7cd4,0x3f5ebe05,0xbefc5d27,0x3f45e403,0xbf226799,0x3f273656,0xbf41d870,0x3f039c3d,0xbf5b941a,0x3eb8442a,0xbf6ed89e,
0x3f800000,0x0,0x3f7cfe73,0xbe1c76de,0x3f740bdd,0xbe9aa086,0x3f655e0b,0xbee363fa,0x3f514d3d,0xbf13682a,0x3f385216,0xbf31a81d,0x3f1b02c6,0xbf4bbbf8,0x3ef41f07,0xbf6106f2,
0x3f800000,0x0,0x3f7bf531,0xbe354098,0x3f6ff573,0xbeb263ef,0x3f5c61c7,0xbf0242b1,0x3f41d870,0xbf273656,0x3f212ff9,0xbf46e22a,0x3ef6e0cb,0xbf604621,0x3ea395c5,0xbf7294f8,
0x3f800000,0x0,0x3f7cbfc9,0xbe22abb6,0x3f731447,0xbea09ae5,0x3f633c5a,0xbeebcbbb,0x3f4d9f02,0xbf187fc0,0x3f32c8c9,0xbf373a23,0x3f13682a,0xbf514d3d,0x3ee0924f,0xbf660f88,
0x3f800000,0x0,0x3f7baccd,0xbe3b6ecf,0x3f6ed89e,0xbeb8442a,0x3f59f26a,0xbf064b82,0x3f3daef9,0xbf2beb4a,0x3f1b02c6,0xbf4bbbf8,0x3ee63375,0xbf64aa59,0x3e8e9a22,0xbf75dec6,
0x3f800000,0x0,0x3f7c7eb0,0xbe28defc,0x3f721352,0xbea68f12,0x3f6106f2,0xbef41f07,0x3f49d112,0xbf1d7fd1,0x3f2d1469,0xbf3ca003,0x3f0b9a6b,0xbf5695e5,0x3ecc9b8b,0xbf6aab7b,
0x3f800000,0x0,0x3f7b61fc,0xbe419b37,0x3f6db293,0xbebe1d4a,0x3f577026,0xbf0a48ad,0x3f396842,0xbf3085bb,0x3f14b039,0xbf5064af,0x3ed53641,0xbf68bf3c,0x3e72b651,0xbf78b47b,
0x3f800000,0x0,0x3f800000,0x0,0x3f800000,0x0,0x3f800000,0x0,0x3f800000,0x0,0x3f800000,0x0,0x3f800000,0x0,0x3f800000,0x0,
0x3f7b14be,0xbe47c5c2,0x3f79c79d,0xbe605c13,0x3f7853f8,0xbe78cfcc,0x3f76ba07,0xbe888e93,0x3f74fa0b,0xbe94a031,0x3f731447,0xbea09ae5,0x3f710908,0xbeac7cd4,0x3f6ed89e,0xbeb8442a,
0x3f7fb10f,0xbd48fb30,0x3f7f9c18,0xbd621469,0x3f7f84ab,0xbd7b2b74,0x3f7f6ac7,0xbd8a200a,0x3f7f4e6d,0xbd96a905,0x3f7f2f9d,0xbda3308c,0x3f7f0e58,0xbdafb680,0x3f7eea9d,0xbdbc3ac3,
0x3f7853f8,0xbe78cfcc,0x3f764d97,0xbe8b9507,0x3f740bdd,0xbe9aa086,0x3f718f57,0xbea986c4,0x3f6ed89e,0xbeb8442a,0x3f6be858,0xbec6d529,0x3f68bf3c,0xbed53641,0x3f655e0b,0xbee363fa,
0x3f7ec46d,0xbdc8bd36,0x3f7e70b0,0xbde1bc2e,0x3f7e1324,0xbdfab273,0x3f7dabcc,0xbe09cf86,0x3f7d3aac,0xbe164083,0x3f7cbfc9,0xbe22abb6,0x3f7c3b28,0xbe2f10a2,0x3f7baccd,0xbe3b6ecf,
0x3f74fa0b,0xbe94a031,0x3f721352,0xbea68f12,0x3f6ed89e,0xbeb8442a,0x3f6b4b0c,0xbec9b953,0x3f676bd8,0xbedae880,0x3f633c5a,0xbeebcbbb,0x3f5ebe05,0xbefc5d27,0x3f59f26a,0xbf064b82,
0x3f7d3aac,0xbe164083,0x3f7c7eb0,0xbe28defc,0x3f7baccd,0xbe3b6ecf,0x3f7ac516,0xbe4dee60,0x3f79c79d,0xbe605c13,0x3f78b47b,0xbe72b651,0x3f778bc5,0xbe827dc0,0x3f764d97,0xbe8b9507,
0x3f710908,0xbeac7cd4,0x3f6d1c1d,0xbec1071e,0x3f68bf3c,0xbed53641,0x3f63f473,0xbee900b7,0x3f5ebe05,0xbefc5d27,0x3f591e6a,0xbf07a136,0x3f531849,0xbf10d3cd,0x3f4cae79,0xbf19c200,
0x3f6c835e,0xbec3ef15,0x3f676bd8,0xbedae880,0x3f61c598,0xbef15aea,0x3f5b941a,0xbf039c3d,0x3f54db31,0xbf0e39da,0x3f4d9f02,0xbf187fc0,0x3f45e403,0xbf226799,0x3f3daef9,0xbf2beb4a,
0x3f54db31,0xbf0e39da,0x3f49d112,0xbf1d7fd1,0x3f3daef9,0xbf2beb4a,0x3f3085bb,0xbf396842,0x3f226799,0xbf45e403,0x3f13682a,0xbf514d3d,0x3f039c3d,0xbf5b941a,0x3ee63375,0xbf64aa59,
0x3f676bd8,0xbedae880,0x3f6106f2,0xbef41f07,0x3f59f26a,0xbf064b82,0x3f5233c6,0xbf121eb0,0x3f49d112,0xbf1d7fd1,0x3f40d0da,0xbf286605,0x3f373a23,0xbf32c8c9,0x3f2d1469,0xbf3ca003,
0x3f4d9f02,0xbf187fc0,0x3f40d0da,0xbf286605,0x3f32c8c9,0xbf373a23,0x3f239da9,0xbf44e3f5,0x3f13682a,0xbf514d3d,0x3f0242b1,0xbf5c61c7,0x3ee0924f,0xbf660f88,0x3ebb31a0,0xbf6e46be,
0x3f61c598,0xbef15aea,0x3f59f26a,0xbf064b82,0x3f514d3d,0xbf13682a,0x3f47de65,0xbf1ff6cb,0x3f3daef9,0xbf2beb4a,0x3f32c8c9,0xbf373a23,0x3f273656,0xbf41d870,0x3f1b02c6,0xbf4bbbf8,
0x3f45e403,0xbf226799,0x3f373a23,0xbf32c8c9,0x3f273656,0xbf41d870,0x3f15f6d9,0xbf4f7a1f,0x3f039c3d,0xbf5b941a,0x3ee0924f,0xbf660f88,0x3eb8442a,0xbf6ed89e,0x3e8e9a22,0xbf75dec6,
0x3f5b941a,0xbf039c3d,0x3f5233c6,0xbf121eb0,0x3f47de65,0xbf1ff6cb,0x3f3ca003,0xbf2d1469,0x3f3085bb,0xbf396842,0x3f239da9,0xbf44e3f5,0x3f15f6d9,0xbf4f7a1f,0x3f07a136,0xbf591e6a,
0x3f3daef9,0xbf2beb4a,0x3f2d1469,0xbf3ca003,0x3f1b02c6,0xbf4bbbf8,0x3f07a136,0xbf591e6a,0x3ee63375,0xbf64aa59,0x3ebb31a0,0xbf6e46be,0x3e8e9a22,0xbf75dec6,0x3e419b37,0xbf7b61fc,
0x3f3504f3,0xbf3504f3,0x3f226799,0xbf45e403,0x3f0e39da,0xbf54db31,0x3ef15aea,0xbf61c598,0x3ec3ef15,0xbf6c835e,0x3e94a031,0xbf74fa0b,0x3e47c5c2,0xbf7b14be,0x3dc8bd36,0xbf7ec46d,
0x3f0e39da,0xbf54db31,0x3ee63375,0xbf64aa59,0x3eac7cd4,0xbf710908,0x3e605c13,0xbf79c79d,0x3dc8bd36,0xbf7ec46d,0xbcc90ab0,0xbf7fec43,0xbe164083,0xbf7d3aac,0xbe888e93,0xbf76ba07,
0x3f2beb4a,0xbf3daef9,0x3f173c07,0xbf4e8d90,0x3f00e7e4,0xbf5d2d53,0x3ed25a09,0xbf696591,0x3ea09ae5,0xbf731447,0x3e5a3997,0xbf7a1e84,0x3de1bc2e,0xbf7e70b0,0x3bc90f88,0xbf7ffec4,
0x3f039c3d,0xbf5b941a,0x3ecc9b8b,0xbf6aab7b,0x3e8e9a22,0xbf75dec6,0x3e1c76de,0xbf7cfe73,0x3cc90ab0,0xbf7fec43,0xbdd53db9,0xbf7e9bc9,0xbe6c9a7f,0xbf791298,0xbeb554ec,0xbf6f6830,
0x3f226799,0xbf45e403,0x3f0b9a6b,0xbf5695e5,0x3ee63375,0xbf64aa59,0x3eb263ef,0xbf6ff573,0x3e78cfcc,0xbf7853f8,0x3e09cf86,0xbf7dabcc,0x3cc90ab0,0xbf7fec43,0xbdafb680,0xbf7f0e58,
0x3ef15aea,0xbf61c598,0x3eb263ef,0xbf6ff573,0x3e605c13,0xbf79c79d,0x3dafb680,0xbf7f0e58,0xbd48fb30,0xbf7fb10f,0xbe3b6ecf,0xbf7baccd,0xbea09ae5,0xbf731447,0xbee0924f,0xbf660f88,
0x3f187fc0,0xbf4d9f02,0x3eff17b2,0xbf5df6be,0x3ec9b953,0xbf6b4b0c,0x3e919ddd,0xbf756d97,0x3e2f10a2,0xbf7c3b28,0x3d621469,0xbf7f9c18,0xbd7b2b74,0xbf7f84ab,0xbe354098,0xbf7bf531,
0x3edae880,0xbf676bd8,0x3e97a117,0xbf748422,0x3e22abb6,0xbf7cbfc9,0x3c96c9b6,0xbf7ff4e6,0xbdfab273,0xbf7e1324,0xbe8586ce,0xbf772417,0xbec9b953,0xbf6b4b0c,0xbf04f484,0xbf5ac450,
0x3ec3ef15,0xbf6c835e,0x3e78cfcc,0xbf7853f8,0x3dc8bd36,0xbf7ec46d,0xbd48fb30,0xbf7fb10f,0xbe47c5c2,0xbf7b14be,0xbeac7cd4,0xbf710908,0xbef15aea,0xbf61c598,0xbf187fc0,0xbf4d9f02,
0x3e47c5c2,0xbf7b14be,0x3cc90ab0,0xbf7fec43,0xbe164083,0xbf7d3aac,0xbea09ae5,0xbf731447,0xbef15aea,0xbf61c598,0xbf1d7fd1,0xbf49d112,0xbf3daef9,0xbf2beb4a,0xbf584853,0xbf08f59b,
0x3eac7cd4,0xbf710908,0x3e419b37,0xbf7b61fc,0x3d16c32c,0xbf7fd397,0xbdee3876,0xbf7e4323,0xbe888e93,0xbf76ba07,0xbed25a09,0xbf696591,0xbf0b9a6b,0xbf5695e5,0xbf2ac082,0xbf3ebc1b,
0x3e164083,0xbf7d3aac,0xbcfb49ba,0xbf7fe129,0xbe541501,0xbf7a7302,0xbec1071e,0xbf6d1c1d,0xbf08f59b,0xbf584853,0xbf2d1469,0xbf3ca003,0xbf4bbbf8,0xbf1b02c6,0xbf63f473,0xbee900b7,
0x3e94a031,0xbf74fa0b,0x3e09cf86,0xbf7dabcc,0xbcc90ab0,0xbf7fec43,0xbe3b6ecf,0xbf7baccd,0xbeac7cd4,0xbf710908,0xbef6e0cb,0xbf604621,0xbf1d7fd1,0xbf49d112,0xbf3b8f3b,0xbf2e3bde,
0x3dc8bd36,0xbf7ec46d,0xbdafb680,0xbf7f0e58,0xbe888e93,0xbf76ba07,0xbee0924f,0xbf660f88,0xbf187fc0,0xbf4d9f02,0xbf3b8f3b,0xbf2e3bde,0xbf584853,0xbf08f59b,0xbf6db293,0xbebe1d4a,
0x3e78cfcc,0xbf7853f8,0x3da3308c,0xbf7f2f9d,0xbdafb680,0xbf7f0e58,0xbe7ee6e1,0xbf77f110,0xbecf7bca,0xbf6a09a7,0xbf0cead0,0xbf55b993,0xbf2e3bde,0xbf3b8f3b,0xbf4ac77f,0xbf1c420c,
0x3d48fb30,0xbf7fb10f,0xbe1008b7,0xbf7d7474,0xbea68f12,0xbf721352,0xbeff17b2,0xbf5df6be,0xbf273656,0xbf41d870,0xbf48d8b3,0xbf1ebc12,0xbf633c5a,0xbeebcbbb,0xbf756d97,0xbe919ddd,
0x3f800000,0x0,0x3f800000,0x0,0x3f800000,0x0,0x3f800000,0x0,0x3f800000,0x0,0x3f800000,0x0,0x3f800000,0x0,0x3f800000,0x0,
0x3f6c835e,0xbec3ef15,0x3f6a09a7,0xbecf7bca,0x3f676bd8,0xbedae880,0x3f64aa59,0xbee63375,0x3f61c598,0xbef15aea,0x3f5ebe05,0xbefc5d27,0x3f5b941a,0xbf039c3d,0x3f584853,0xbf08f59b,
0x3f7ec46d,0xbdc8bd36,0x3f7e9bc9,0xbdd53db9,0x3f7e70b0,0xbde1bc2e,0x3f7e4323,0xbdee3876,0x3f7e1324,0xbdfab273,0x3f7de0b1,0xbe039502,0x3f7dabcc,0xbe09cf86,0x3f7d7474,0xbe1008b7,
0x3f61c598,0xbef15aea,0x3f5df6be,0xbeff17b2,0x3f59f26a,0xbf064b82,0x3f55b993,0xbf0cead0,0x3f514d3d,0xbf13682a,0x3f4cae79,0xbf19c200,0x3f47de65,0xbf1ff6cb,0x3f42de29,0xbf26050a,
0x3f7b14be,0xbe47c5c2,0x3f7a7302,0xbe541501,0x3f79c79d,0xbe605c13,0x3f791298,0xbe6c9a7f,0x3f7853f8,0xbe78cfcc,0x3f778bc5,0xbe827dc0,0x3f76ba07,0xbe888e93,0x3f75dec6,0xbe8e9a22,
0x3f54db31,0xbf0e39da,0x3f4f7a1f,0xbf15f6d9,0x3f49d112,0xbf1d7fd1,0x3f43e200,0xbf24d225,0x3f3daef9,0xbf2beb4a,0x3f373a23,0xbf32c8c9,0x3f3085bb,0xbf396842,0x3f299415,0xbf3fc767,
0x3f74fa0b,0xbe94a031,0x3f73913f,0xbe9d9e78,0x3f721352,0xbea68f12,0x3f708066,0xbeaf713a,0x3f6ed89e,0xbeb8442a,0x3f6d1c1d,0xbec1071e,0x3f6b4b0c,0xbec9b953,0x3f696591,0xbed25a09,
0x3f45e403,0xbf226799,0x3f3ebc1b,0xbf2ac082,0x3f373a23,0xbf32c8c9,0x3f2f61a5,0xbf3a7ca4,0x3f273656,0xbf41d870,0x3f1ebc12,0xbf48d8b3,0x3f15f6d9,0xbf4f7a1f,0x3f0cead0,0xbf55b993,
0x3f3504f3,0xbf3504f3,0x3f2beb4a,0xbf3daef9,0x3f226799,0xbf45e403,0x3f187fc0,0xbf4d9f02,0x3f0e39da,0xbf54db31,0x3f039c3d,0xbf5b941a,0x3ef15aea,0xbf61c598,0x3edae880,0xbf676bd8,
0x3ec3ef15,0xbf6c835e,0x3ea09ae5,0xbf731447,0x3e78cfcc,0xbf7853f8,0x3e2f10a2,0xbf7c3b28,0x3dc8bd36,0xbf7ec46d,0x3cc90ab0,0xbf7fec43,0xbd48fb30,0xbf7fb10f,0xbdfab273,0xbf7e1324,
0x3f226799,0xbf45e403,0x3f173c07,0xbf4e8d90,0x3f0b9a6b,0xbf5695e5,0x3eff17b2,0xbf5df6be,0x3ee63375,0xbf64aa59,0x3ecc9b8b,0xbf6aab7b,0x3eb263ef,0xbf6ff573,0x3e97a117,0xbf748422,
0x3e94a031,0xbf74fa0b,0x3e5a3997,0xbf7a1e84,0x3e09cf86,0xbf7dabcc,0x3d621469,0xbf7f9c18,0xbcc90ab0,0xbf7fec43,0xbdd53db9,0xbf7e9bc9,0xbe3b6ecf,0xbf7baccd,0xbe8586ce,0xbf772417,
0x3f0e39da,0xbf54db31,0x3f00e7e4,0xbf5d2d53,0x3ee63375,0xbf64aa59,0x3ec9b953,0xbf6b4b0c,0x3eac7cd4,0xbf710908,0x3e8e9a22,0xbf75dec6,0x3e605c13,0xbf79c79d,0x3e22abb6,0xbf7cbfc9,
0x3e47c5c2,0xbf7b14be,0x3de1bc2e,0xbf7e70b0,0x3cc90ab0,0xbf7fec43,0xbd7b2b74,0xbf7f84ab,0xbe164083,0xbf7d3aac,0xbe6c9a7f,0xbf791298,0xbea09ae5,0xbf731447,0xbec9b953,0xbf6b4b0c,
0x3ef15aea,0xbf61c598,0x3ed25a09,0xbf696591,0x3eb263ef,0xbf6ff573,0x3e919ddd,0xbf756d97,0x3e605c13,0xbf79c79d,0x3e1c76de,0xbf7cfe73,0x3dafb680,0xbf7f0e58,0x3c96c9b6,0xbf7ff4e6,
0x3dc8bd36,0xbf7ec46d,0x3bc90f88,0xbf7ffec4,0xbdafb680,0xbf7f0e58,0xbe354098,0xbf7bf531,0xbe888e93,0xbf76ba07,0xbeb554ec,0xbf6f6830,0xbee0924f,0xbf660f88,0xbf04f484,0xbf5ac450,
0x0,0xbf800000,0xbdc8bd36,0xbf7ec46d,0xbe47c5c2,0xbf7b14be,0xbe94a031,0xbf74fa0b,0xbec3ef15,0xbf6c835e,0xbef15aea,0xbf61c598,0xbf0e39da,0xbf54db31,0xbf226799,0xbf45e403,
0xbec3ef15,0xbf6c835e,0xbefc5d27,0xbf5ebe05,0xbf187fc0,0xbf4d9f02,0xbf3085bb,0xbf396842,0xbf45e403,0xbf226799,0xbf584853,0xbf08f59b,0xbf676bd8,0xbedae880,0xbf731447,0xbea09ae5,
0xbdc8bd36,0xbf7ec46d,0xbe4dee60,0xbf7ac516,0xbe9aa086,0xbf740bdd,0xbecc9b8b,0xbf6aab7b,0xbefc5d27,0xbf5ebe05,0xbf14b039,0xbf5064af,0xbf299415,0xbf3fc767,0xbf3ca003,0xbf2d1469,
0xbef15aea,0xbf61c598,0xbf14b039,0xbf5064af,0xbf2e3bde,0xbf3b8f3b,0xbf44e3f5,0xbf239da9,0xbf584853,0xbf08f59b,0xbf6816a8,0xbed8106b,0xbf740bdd,0xbe9aa086,0xbf7bf531,0xbe354098,
0xbe47c5c2,0xbf7b14be,0xbe9aa086,0xbf740bdd,0xbecf7bca,0xbf6a09a7,0xbf00e7e4,0xbf5d2d53,0xbf187fc0,0xbf4d9f02,0xbf2e3bde,0xbf3b8f3b,0xbf41d870,0xbf273656,0xbf531849,0xbf10d3cd,
0xbf0e39da,0xbf54db31,0xbf299415,0xbf3fc767,0xbf41d870,0xbf273656,0xbf5695e5,0xbf0b9a6b,0xbf676bd8,0xbedae880,0xbf740bdd,0xbe9aa086,0xbf7c3b28,0xbe2f10a2,0xbf7fd397,0xbd16c32c,
0xbe94a031,0xbf74fa0b,0xbecc9b8b,0xbf6aab7b,0xbf00e7e4,0xbf5d2d53,0xbf19c200,0xbf4cae79,0xbf3085bb,0xbf396842,0xbf44e3f5,0xbf239da9,0xbf5695e5,0xbf0b9a6b,0xbf655e0b,0xbee363fa,
0xbf226799,0xbf45e403,0xbf3ca003,0xbf2d1469,0xbf531849,0xbf10d3cd,0xbf655e0b,0xbee363fa,0xbf731447,0xbea09ae5,0xbf7bf531,0xbe354098,0xbf7fd397,0xbd16c32c,0xbf7e9bc9,0x3dd53db9,
0xbf3504f3,0xbf3504f3,0xbf4d9f02,0xbf187fc0,0xbf61c598,0xbef15aea,0xbf710908,0xbeac7cd4,0xbf7b14be,0xbe47c5c2,0xbf7fb10f,0xbd48fb30,0xbf7ec46d,0x3dc8bd36,0xbf7853f8,0x3e78cfcc,
0xbf6c835e,0xbec3ef15,0xbf79c79d,0xbe605c13,0xbf7fb10f,0xbd48fb30,0xbf7e1324,0x3dfab273,0xbf74fa0b,0x3e94a031,0xbf64aa59,0x3ee63375,0xbf4d9f02,0x3f187fc0,0xbf3085bb,0x3f396842,
0xbf45e403,0xbf226799,0xbf5c61c7,0xbf0242b1,0xbf6db293,0xbebe1d4a,0xbf796e4e,0xbe667c66,0xbf7f4e6d,0xbd96a905,0xbf7f2f9d,0x3da3308c,0xbf791298,0x3e6c9a7f,0xbf6d1c1d,0x3ec1071e,
0xbf74fa0b,0xbe94a031,0xbf7e4323,0xbdee3876,0xbf7f84ab,0x3d7b2b74,0xbf78b47b,0x3e72b651,0xbf6a09a7,0x3ecf7bca,0xbf53fac3,0x3f0f8784,0xbf373a23,0x3f32c8c9,0xbf14b039,0x3f5064af,
0xbf54db31,0xbf0e39da,0xbf68bf3c,0xbed53641,0xbf76ba07,0xbe888e93,0xbf7e70b0,0xbde1bc2e,0xbf7fb10f,0x3d48fb30,0xbf7a7302,0x3e541501,0xbf6ed89e,0x3eb8442a,0xbf5d2d53,0x3f00e7e4,
0xbf7b14be,0xbe47c5c2,0xbf7ffb11,0xbc490e90,0xbf7c3b28,0x3e2f10a2,0xbf6ff573,0x3eb263ef,0xbf5b941a,0x3f039c3d,0xbf3fc767,0x3f299415,0xbf1d7fd1,0x3f49d112,0xbeebcbbb,0x3f633c5a,
0xbf61c598,0xbef15aea,0xbf7294f8,0xbea395c5,0xbf7cbfc9,0xbe22abb6,0xbf7ffec4,0x3bc90f88,0xbf7c3b28,0x3e2f10a2,0xbf718f57,0x3ea986c4,0xbf604621,0x3ef6e0cb,0xbf48d8b3,0x3f1ebc12,
0xbf7ec46d,0xbdc8bd36,0xbf7eea9d,0x3dbc3ac3,0xbf75dec6,0x3e8e9a22,0xbf63f473,0x3ee900b7,0xbf49d112,0x3f1d7fd1,0xbf286605,0x3f40d0da,0xbf00e7e4,0x3f5d2d53,0xbea986c4,0x3f718f57,
0x3f800000,0x0,0x3f800000,0x0,0x3f800000,0x0,0x3f800000,0x0,0x3f800000,0x0,0x3f800000,0x0,0x3f800000,0x0,0x3f800000,0x0,
0x3f54db31,0xbf0e39da,0x3f514d3d,0xbf13682a,0x3f4d9f02,0xbf187fc0,0x3f49d112,0xbf1d7fd1,0x3f45e403,0xbf226799,0x3f41d870,0xbf273656,0x3f3daef9,0xbf2beb4a,0x3f396842,0xbf3085bb,
0x3f7d3aac,0xbe164083,0x3f7cfe73,0xbe1c76de,0x3f7cbfc9,0xbe22abb6,0x3f7c7eb0,0xbe28defc,0x3f7c3b28,0xbe2f10a2,0x3f7bf531,0xbe354098,0x3f7baccd,0xbe3b6ecf,0x3f7b61fc,0xbe419b37,
0x3f3daef9,0xbf2beb4a,0x3f385216,0xbf31a81d,0x3f32c8c9,0xbf373a23,0x3f2d1469,0xbf3ca003,0x3f273656,0xbf41d870,0x3f212ff9,0xbf46e22a,0x3f1b02c6,0xbf4bbbf8,0x3f14b039,0xbf5064af,
0x3f74fa0b,0xbe94a031,0x3f740bdd,0xbe9aa086,0x3f731447,0xbea09ae5,0x3f721352,0xbea68f12,0x3f710908,0xbeac7cd4,0x3f6ff573,0xbeb263ef,0x3f6ed89e,0xbeb8442a,0x3f6db293,0xbebe1d4a,
0x3f226799,0xbf45e403,0x3f1b02c6,0xbf4bbbf8,0x3f13682a,0xbf514d3d,0x3f0b9a6b,0xbf5695e5,0x3f039c3d,0xbf5b941a,0x3ef6e0cb,0xbf604621,0x3ee63375,0xbf64aa59,0x3ed53641,0xbf68bf3c,
0x3f676bd8,0xbedae880,0x3f655e0b,0xbee363fa,0x3f633c5a,0xbeebcbbb,0x3f6106f2,0xbef41f07,0x3f5ebe05,0xbefc5d27,0x3f5c61c7,0xbf0242b1,0x3f59f26a,0xbf064b82,0x3f577026,0xbf0a48ad,
0x3f039c3d,0xbf5b941a,0x3ef41f07,0xbf6106f2,0x3ee0924f,0xbf660f88,0x3ecc9b8b,0xbf6aab7b,0x3eb8442a,0xbf6ed89e,0x3ea395c5,0xbf7294f8,0x3e8e9a22,0xbf75dec6,0x3e72b651,0xbf78b47b,
0x3ec3ef15,0xbf6c835e,0x3eac7cd4,0xbf710908,0x3e94a031,0xbf74fa0b,0x3e78cfcc,0xbf7853f8,0x3e47c5c2,0xbf7b14be,0x3e164083,0xbf7d3aac,0x3dc8bd36,0xbf7ec46d,0x3d48fb30,0xbf7fb10f,
0xbe47c5c2,0xbf7b14be,0xbe888e93,0xbf76ba07,0xbeac7cd4,0xbf710908,0xbecf7bca,0xbf6a09a7,0xbef15aea,0xbf61c598,0xbf08f59b,0xbf584853,0xbf187fc0,0xbf4d9f02,0xbf273656,0xbf41d870,
0x3e78cfcc,0xbf7853f8,0x3e419b37,0xbf7b61fc,0x3e09cf86,0xbf7dabcc,0x3da3308c,0xbf7f2f9d,0x3cc90ab0,0xbf7fec43,0xbcfb49ba,0xbf7fe129,0xbdafb680,0xbf7f0e58,0xbe1008b7,0xbf7d7474,
0xbeac7cd4,0xbf710908,0xbed25a09,0xbf696591,0xbef6e0cb,0xbf604621,0xbf0cead0,0xbf55b993,0xbf1d7fd1,0xbf49d112,0xbf2d1469,0xbf3ca003,0xbf3b8f3b,0xbf2e3bde,0xbf48d8b3,0xbf1ebc12,
0x3dc8bd36,0xbf7ec46d,0x3d16c32c,0xbf7fd397,0xbcc90ab0,0xbf7fec43,0xbdafb680,0xbf7f0e58,0xbe164083,0xbf7d3aac,0xbe541501,0xbf7a7302,0xbe888e93,0xbf76ba07,0xbea68f12,0xbf721352,
0xbef15aea,0xbf61c598,0xbf0b9a6b,0xbf5695e5,0xbf1d7fd1,0xbf49d112,0xbf2e3bde,0xbf3b8f3b,0xbf3daef9,0xbf2beb4a,0xbf4bbbf8,0xbf1b02c6,0xbf584853,0xbf08f59b,0xbf633c5a,0xbeebcbbb,
0xbd48fb30,0xbf7fb10f,0xbdee3876,0xbf7e4323,0xbe3b6ecf,0xbf7baccd,0xbe7ee6e1,0xbf77f110,0xbea09ae5,0xbf731447,0xbec1071e,0xbf6d1c1d,0xbee0924f,0xbf660f88,0xbeff17b2,0xbf5df6be,
0xbf187fc0,0xbf4d9f02,0xbf2ac082,0xbf3ebc1b,0xbf3b8f3b,0xbf2e3bde,0xbf4ac77f,0xbf1c420c,0xbf584853,0xbf08f59b,0xbf63f473,0xbee900b7,0xbf6db293,0xbebe1d4a,0xbf756d97,0xbe919ddd,
0xbf3504f3,0xbf3504f3,0xbf45e403,0xbf226799,0xbf54db31,0xbf0e39da,0xbf61c598,0xbef15aea,0xbf6c835e,0xbec3ef15,0xbf74fa0b,0xbe94a031,0xbf7b14be,0xbe47c5c2,0xbf7ec46d,0xbdc8bd36,
0xbf7b14be,0xbe47c5c2,0xbf7f4e6d,0xbd96a905,0xbf7fb10f,0x3d48fb30,0xbf7c3b28,0x3e2f10a2,0xbf74fa0b,0x3e94a031,0xbf6a09a7,0x3ecf7bca,0xbf5b941a,0x3f039c3d,0xbf49d112,0x3f1d7fd1,
0xbf4d9f02,0xbf187fc0,0xbf5c61c7,0xbf0242b1,0xbf68bf3c,0xbed53641,0xbf7294f8,0xbea395c5,0xbf79c79d,0xbe605c13,0xbf7e4323,0xbdee3876,0xbf7ffb11,0xbc490e90,0xbf7eea9d,0x3dbc3ac3,
0xbf7fb10f,0xbd48fb30,0xbf7f2f9d,0x3da3308c,0xbf7a7302,0x3e541501,0xbf718f57,0x3ea986c4,0xbf64aa59,0x3ee63375,0xbf53fac3,0x3f0f8784,0xbf3fc767,0x3f299415,0xbf286605,0x3f40d0da,
0xbf61c598,0xbef15aea,0xbf6db293,0xbebe1d4a,0xbf76ba07,0xbe888e93,0xbf7cbfc9,0xbe22abb6,0xbf7fb10f,0xbd48fb30,0xbf7f84ab,0x3d7b2b74,0xbf7c3b28,0x3e2f10a2,0xbf75dec6,0x3e8e9a22,
0xbf7ec46d,0x3dc8bd36,0xbf791298,0x3e6c9a7f,0xbf6ed89e,0x3eb8442a,0xbf604621,0x3ef6e0cb,0xbf4d9f02,0x3f187fc0,0xbf373a23,0x3f32c8c9,0xbf1d7fd1,0x3f49d112,0xbf00e7e4,0x3f5d2d53,
0xbf710908,0xbeac7cd4,0xbf796e4e,0xbe667c66,0xbf7e70b0,0xbde1bc2e,0xbf7ffec4,0x3bc90f88,0xbf7e1324,0x3dfab273,0xbf78b47b,0x3e72b651,0xbf6ff573,0x3eb263ef,0xbf63f473,0x3ee900b7,
0xbf7853f8,0x3e78cfcc,0xbf6d1c1d,0x3ec1071e,0xbf5d2d53,0x3f00e7e4,0xbf48d8b3,0x3f1ebc12,0xbf3085bb,0x3f396842,0xbf14b039,0x3f5064af,0xbeebcbbb,0x3f633c5a,0xbea986c4,0x3f718f57,
0xbf6c835e,0x3ec3ef15,0xbf5b941a,0x3f039c3d,0xbf45e403,0x3f226799,0xbf2beb4a,0x3f3daef9,0xbf0e39da,0x3f54db31,0xbedae880,0x3f676bd8,0xbe94a031,0x3f74fa0b,0xbe164083,0x3f7d3aac,
0xbf0e39da,0x3f54db31,0xbecf7bca,0x3f6a09a7,0xbe78cfcc,0x3f7853f8,0xbd96a905,0x3f7f4e6d,0x3dc8bd36,0x3f7ec46d,0x3e888e93,0x3f76ba07,0x3edae880,0x3f676bd8,0x3f13682a,0x3f514d3d,
0xbf5b941a,0x3f039c3d,0xbf44e3f5,0x3f239da9,0xbf299415,0x3f3fc767,0xbf0a48ad,0x3f577026,0xbecf7bca,0x3f6a09a7,0xbe8586ce,0x3f772417,0xbde1bc2e,0x3f7e70b0,0x3d2fe007,0x3f7fc38f,
0xbedae880,0x3f676bd8,0xbe8586ce,0x3f772417,0xbdafb680,0x3f7f0e58,0x3dbc3ac3,0x3f7eea9d,0x3e888e93,0x3f76ba07,0x3eddbe79,0x3f66becc,0x3f15f6d9,0x3f4f7a1f,0x3f385216,0x3f31a81d,
0xbf45e403,0x3f226799,0xbf299415,0x3f3fc767,0xbf08f59b,0x3f584853,0xbec9b953,0x3f6b4b0c,0xbe78cfcc,0x3f7853f8,0xbdafb680,0x3f7f0e58,0x3d96a905,0x3f7f4e6d,0x3e6c9a7f,0x3f791298,
0xbe94a031,0x3f74fa0b,0xbde1bc2e,0x3f7e70b0,0x3d96a905,0x3f7f4e6d,0x3e827dc0,0x3f778bc5,0x3edae880,0x3f676bd8,0x3f15f6d9,0x3f4f7a1f,0x3f396842,0x3f3085bb,0x3f5695e5,0x3f0b9a6b,
0xbf2beb4a,0x3f3daef9,0xbf0a48ad,0x3f577026,0xbec9b953,0x3f6b4b0c,0xbe72b651,0x3f78b47b,0xbd96a905,0x3f7f4e6d,0x3dbc3ac3,0x3f7eea9d,0x3e827dc0,0x3f778bc5,0x3ed25a09,0x3f696591,
0xbe164083,0x3f7d3aac,0x3d2fe007,0x3f7fc38f,0x3e6c9a7f,0x3f791298,0x3ed25a09,0x3f696591,0x3f13682a,0x3f514d3d,0x3f385216,0x3f31a81d,0x3f5695e5,0x3f0b9a6b,0x3f6d1c1d,0x3ec1071e,
0x3e00,0x3e00,0x3e00,0x3e00,0x3e00,0x3e00,0x3e00,0x3e00,0x3e00,0x3e00,0x3e00,0x3e00,0x3e00,0x3e00,0x3e00,0x3e00,
0xbd443ded,0xbcc83dfb,0xbc493dff,0xbd153df5,0xbdb53db5,0xbdd53d8e,0xbdc63da2,0xbde23d71,0xbe000000,0xbdfbbcc8,0xbdffbc49,0xbdf5bd15,0xbdb5bdb5,0xbd8ebdd5,0xbda2bdc6,0xbd71bde2,
0xbdb53db5,0xbd443ded,0xbcc83dfb,0xbd8e3dd5,0xbe000000,0xbdedbd44,0xbdfbbcc8,0xbdd5bd8e,0xbe00,0x3d44bded,0x3cc8bdfb,0x3d8ebdd5,0x3e000000,0x3ded3d44,0x3dfb3cc8,0x3dd53d8e,
0xbded3d44,0xbd8e3dd5,0xbd153df5,0xbdc63da2,0xbdb5bdb5,0xbcc8bdfb,0xbd71bde2,0x3c49bdff,0x3e000000,0x3dd53d8e,0x3df53d15,0x3da23dc6,0xbdb53db5,0xbdfb3cc8,0xbde23d71,0xbdffbc49,
0xbe000000,0xbdb53db5,0xbd443ded,0xbded3d44,0xbe00,0x3db5bdb5,0x3d44bded,0x3dedbd44,0x3e00,0xbdb53db5,0xbd443ded,0xbded3d44,0xbe00,0x3db5bdb5,0x3d44bded,0x3dedbd44,
0xbdedbd44,0xbdd53d8e,0xbd713de2,0xbdff3c49,0x3db5bdb5,0x3dfb3cc8,0x3df5bd15,0x3dc63da2,0xbe000000,0xbd8ebdd5,0xbde2bd71,0xbc49bdff,0x3db53db5,0xbcc83dfb,0x3d153df5,0xbda23dc6,
0xbdb5bdb5,0xbded3d44,0xbd8e3dd5,0xbdfbbcc8,0x3e000000,0x3d443ded,0x3dd53d8e,0xbcc83dfb,0xbe00,0x3dedbd44,0x3d8ebdd5,0x3dfb3cc8,0xbe000000,0xbd44bded,0xbdd5bd8e,0x3cc8bdfb,
0xbd44bded,0xbdfb3cc8,0xbda23dc6,0xbde2bd71,0x3db53db5,0xbd8e3dd5,0x3c493dff,0xbdf53d15,0x3e000000,0x3cc83dfb,0x3dc63da2,0xbd713de2,0x3db5bdb5,0x3dd53d8e,0x3dffbc49,0x3d153df5,
0xbe00,0xbe000000,0xbdb53db5,0xbdb5bdb5,0x3e00,0xbe000000,0xbdb53db5,0xbdb5bdb5,0x3e00,0xbe000000,0xbdb53db5,0xbdb5bdb5,0x3e00,0xbe000000,0xbdb53db5,0xbdb5bdb5,
0x3d44bded,0xbdfbbcc8,0xbdc63da2,0xbd71bde2,0xbdb53db5,0xbd8ebdd5,0xbdffbc49,0x3d15bdf5,0xbe000000,0x3cc8bdfb,0xbda2bdc6,0x3de2bd71,0xbdb5bdb5,0x3dd5bd8e,0x3c49bdff,0x3df53d15,
0x3db5bdb5,0xbdedbd44,0xbdd53d8e,0xbcc8bdfb,0xbe000000,0x3d44bded,0xbd8ebdd5,0x3dfbbcc8,0xbe00,0x3ded3d44,0x3dd5bd8e,0x3cc83dfb,0x3e000000,0xbd443ded,0x3d8e3dd5,0xbdfb3cc8,
0x3dedbd44,0xbdd5bd8e,0xbde23d71,0x3c49bdff,0xbdb5bdb5,0x3dfbbcc8,0x3d15bdf5,0x3da23dc6,0x3e000000,0xbd8e3dd5,0x3d713de2,0xbdffbc49,0xbdb53db5,0xbcc8bdfb,0xbdf5bd15,0x3dc6bda2,
0x3e000000,0xbdb5bdb5,0xbded3d44,0x3d44bded,0xbe00,0x3db53db5,0x3dedbd44,0xbd443ded,0x3e00,0xbdb5bdb5,0xbded3d44,0x3d44bded,0xbe00,0x3db53db5,0x3dedbd44,0xbd443ded,
0x3ded3d44,0xbd8ebdd5,0xbdf53d15,0x3da2bdc6,0x3db5bdb5,0xbcc83dfb,0x3de23d71,0xbdff3c49,0xbe000000,0x3dd5bd8e,0xbd15bdf5,0x3dc63da2,0x3db53db5,0xbdfbbcc8,0xbd713de2,0xbc49bdff,
0x3db53db5,0xbd44bded,0xbdfb3cc8,0x3dd5bd8e,0x3e000000,0xbded3d44,0x3cc83dfb,0xbd8ebdd5,0xbe00,0x3d443ded,0x3dfbbcc8,0xbdd53d8e,0xbe000000,0x3dedbd44,0xbcc8bdfb,0x3d8e3dd5,
0x3d443ded,0xbcc8bdfb,0xbdff3c49,0x3df5bd15,0x3db53db5,0xbdd5bd8e,0xbda23dc6,0x3d71bde2,0x3e000000,0xbdfb3cc8,0x3c493dff,0xbd15bdf5,0x3db5bdb5,0xbd8e3dd5,0x3dc63da2,0xbde2bd71,
0x3e00,0xbe00,0xbe000000,0x3e000000,0x3e00,0xbe00,0xbe000000,0x3e000000,0x3e00,0xbe00,0xbe000000,0x3e000000,0x3e00,0xbe00,0xbe000000,0x3e000000,
0xbd443ded,0x3cc8bdfb,0xbdffbc49,0x3df53d15,0xbdb53db5,0x3dd5bd8e,0xbda2bdc6,0x3d713de2,0xbe000000,0x3dfb3cc8,0x3c49bdff,0xbd153df5,0xbdb5bdb5,0x3d8e3dd5,0x3dc6bda2,0xbde23d71,
0xbdb53db5,0x3d44bded,0xbdfbbcc8,0x3dd53d8e,0xbe000000,0x3ded3d44,0x3cc8bdfb,0xbd8e3dd5,0xbe00,0xbd443ded,0x3dfb3cc8,0xbdd5bd8e,0x3e000000,0xbdedbd44,0xbcc83dfb,0x3d8ebdd5,
0xbded3d44,0x3d8ebdd5,0xbdf5bd15,0x3da23dc6,0xbdb5bdb5,0x3cc83dfb,0x3de2bd71,0xbdffbc49,0x3e000000,0xbdd5bd8e,0xbd153df5,0x3dc6bda2,0xbdb53db5,0x3dfbbcc8,0xbd71bde2,0xbc493dff,
0xbe000000,0x3db5bdb5,0xbdedbd44,0x3d443ded,0xbe00,0xbdb53db5,0x3ded3d44,0xbd44bded,0x3e00,0x3db5bdb5,0xbdedbd44,0x3d443ded,0xbe00,0xbdb53db5,0x3ded3d44,0xbd44bded,
0xbdedbd44,0x3dd5bd8e,0xbde2bd71,0x3c493dff,0x3db5bdb5,0xbdfbbcc8,0x3d153df5,0x3da2bdc6,0xbe000000,0x3d8e3dd5,0x3d71bde2,0xbdff3c49,0x3db53db5,0x3cc8bdfb,0xbdf53d15,0x3dc63da2,
0xbdb5bdb5,0x3dedbd44,0xbdd5bd8e,0xbcc83dfb,0x3e000000,0xbd44bded,0xbd8e3dd5,0x3dfb3cc8,0xbe00,0xbded3d44,0x3dd53d8e,0x3cc8bdfb,0xbe000000,0x3d443ded,0x3d8ebdd5,0xbdfbbcc8,
0xbd44bded,0x3dfbbcc8,0xbdc6bda2,0xbd713de2,0x3db53db5,0x3d8ebdd5,0xbdff3c49,0x3d153df5,0x3e000000,0xbcc8bdfb,0xbda23dc6,0x3de23d71,0x3db5bdb5,0xbdd5bd8e,0x3c493dff,0x3df5bd15,
0xbe00,0x3e000000,0xbdb5bdb5,0xbdb53db5,0x3e00,0x3e000000,0xbdb5bdb5,0xbdb53db5,0x3e00,0x3e000000,0xbdb5bdb5,0xbdb53db5,0x3e00,0x3e000000,0xbdb5bdb5,0xbdb53db5,
0x3d44bded,0x3dfb3cc8,0xbda2bdc6,0xbde23d71,0xbdb53db5,0x3d8e3dd5,0x3c49bdff,0xbdf5bd15,0xbe000000,0xbcc83dfb,0x3dc6bda2,0xbd71bde2,0xbdb5bdb5,0xbdd53d8e,0x3dff3c49,0x3d15bdf5,
0x3db5bdb5,0x3ded3d44,0xbd8ebdd5,0xbdfb3cc8,0xbe000000,0xbd443ded,0x3dd5bd8e,0xbcc8bdfb,0xbe00,0xbdedbd44,0x3d8e3dd5,0x3dfbbcc8,0x3e000000,0x3d44bded,0xbdd53d8e,0x3cc83dfb,
0x3dedbd44,0x3dd53d8e,0xbd71bde2,0xbdffbc49,0xbdb5bdb5,0xbdfb3cc8,0x3df53d15,0x3dc6bda2,0x3e000000,0x3d8ebdd5,0xbde23d71,0xbc493dff,0xbdb53db5,0x3cc83dfb,0x3d15bdf5,0xbda2bdc6,
0x3e000000,0x3db53db5,0xbd44bded,0xbdedbd44,0xbe00,0xbdb5bdb5,0x3d443ded,0x3ded3d44,0x3e00,0x3db53db5,0xbd44bded,0xbdedbd44,0xbe00,0xbdb5bdb5,0x3d443ded,0x3ded3d44,
0x3ded3d44,0x3d8e3dd5,0xbd15bdf5,0xbdc6bda2,0x3db5bdb5,0x3cc8bdfb,0xbd713de2,0x3c493dff,0xbe000000,0xbdd53d8e,0x3df5bd15,0x3da2bdc6,0x3db53db5,0x3dfb3cc8,0xbde2bd71,0xbdff3c49,
0x3db53db5,0x3d443ded,0xbcc8bdfb,0xbd8ebdd5,0x3e000000,0x3dedbd44,0xbdfb3cc8,0xbdd53d8e,0xbe00,0xbd44bded,0x3cc83dfb,0x3d8e3dd5,0xbe000000,0xbded3d44,0x3dfbbcc8,0x3dd5bd8e,
0x3d443ded,0x3cc83dfb,0xbc49bdff,0xbd15bdf5,0x3db53db5,0x3dd53d8e,0xbdc6bda2,0xbde2bd71,0x3e000000,0x3dfbbcc8,0xbdff3c49,0xbdf53d15,0x3db5bdb5,0x3d8ebdd5,0xbda23dc6,0xbd713de2,
0x3d803d80,0x3e00,0x3e00,0x3e00,0x3e00,0x3e00,0x3e00,0x3e00,0x3e00,0x3e00,0x3e00,0x3e00,0x3e00,0x3e00,0x3e00,0x3e00,
0xbd803d80,0x3cc8bdfb,0x3c49bdff,0x3d15bdf5,0xbded3d44,0x3dd5bd8e,0x3dc6bda2,0x3de2bd71,0xbdedbd44,0x3dfb3cc8,0x3dff3c49,0x3df53d15,0xbd44bded,0x3d8e3dd5,0x3da23dc6,0x3d713de2,
0x3d803d80,0xbd443ded,0xbcc83dfb,0xbd8e3dd5,0xbdb5bdb5,0xbdedbd44,0xbdfbbcc8,0xbdd5bd8e,0x3db5bdb5,0x3d44bded,0x3cc8bdfb,0x3d8ebdd5,0x3db53db5,0x3ded3d44,0x3dfb3cc8,0x3dd53d8e,
0xbd803d80,0x3d8ebdd5,0x3d15bdf5,0x3dc6bda2,0x3d44bded,0x3cc83dfb,0x3d713de2,0xbc493dff,0x3d443ded,0xbdd5bd8e,0xbdf5bd15,0xbda2bdc6,0xbdedbd44,0x3dfbbcc8,0x3de2bd71,0x3dff3c49,
0x3d803d80,0xbdb53db5,0xbd443ded,0xbded3d44,0x3e000000,0x3db5bdb5,0x3d44bded,0x3dedbd44,0xbe000000,0xbdb53db5,0xbd443ded,0xbded3d44,0x3e000000,0x3db5bdb5,0x3d44bded,0x3dedbd44,
0xbd803d80,0x3dd5bd8e,0x3d71bde2,0x3dffbc49,0x3d443ded,0xbdfbbcc8,0xbdf53d15,0xbdc6bda2,0x3d44bded,0x3d8e3dd5,0x3de23d71,0x3c493dff,0xbded3d44,0x3cc8bdfb,0xbd15bdf5,0x3da2bdc6,
0x3d803d80,0xbded3d44,0xbd8e3dd5,0xbdfbbcc8,0xbdb53db5,0x3d443ded,0x3dd53d8e,0xbcc83dfb,0x3db53db5,0x3dedbd44,0x3d8ebdd5,0x3dfb3cc8,0x3db5bdb5,0xbd44bded,0xbdd5bd8e,0x3cc8bdfb,
0xbd803d80,0x3dfbbcc8,0x3da2bdc6,0x3de23d71,0xbdedbd44,0x3d8ebdd5,0xbc49bdff,0x3df5bd15,0xbded3d44,0xbcc8bdfb,0xbdc6bda2,0x3d71bde2,0xbd443ded,0xbdd5bd8e,0xbdff3c49,0xbd15bdf5,
0x3d803d80,0xbe000000,0xbdb53db5,0xbdb5bdb5,0xbe00,0xbe000000,0xbdb53db5,0xbdb5bdb5,0xbe00,0xbe000000,0xbdb53db5,0xbdb5bdb5,0xbe00,0xbe000000,0xbdb53db5,0xbdb5bdb5,
0xbd803d80,0x3dfb3cc8,0x3dc6bda2,0x3d713de2,0x3dedbd44,0x3d8e3dd5,0x3dff3c49,0xbd153df5,0x3ded3d44,0xbcc83dfb,0x3da23dc6,0xbde23d71,0x3d443ded,0xbdd53d8e,0xbc493dff,0xbdf5bd15,
0x3d803d80,0xbdedbd44,0xbdd53d8e,0xbcc8bdfb,0x3db53db5,0x3d44bded,0xbd8ebdd5,0x3dfbbcc8,0xbdb53db5,0x3ded3d44,0x3dd5bd8e,0x3cc83dfb,0xbdb5bdb5,0xbd443ded,0x3d8e3dd5,0xbdfb3cc8,
0xbd803d80,0x3dd53d8e,0x3de2bd71,0xbc493dff,0xbd443ded,0xbdfb3cc8,0xbd153df5,0xbda2bdc6,0xbd44bded,0x3d8ebdd5,0xbd71bde2,0x3dff3c49,0x3ded3d44,0x3cc83dfb,0x3df53d15,0xbdc63da2,
0x3d803d80,0xbdb5bdb5,0xbded3d44,0x3d44bded,0xbe000000,0x3db53db5,0x3dedbd44,0xbd443ded,0x3e000000,0xbdb5bdb5,0xbded3d44,0x3d44bded,0xbe000000,0x3db53db5,0x3dedbd44,0xbd443ded,
0xbd803d80,0x3d8e3dd5,0x3df5bd15,0xbda23dc6,0xbd44bded,0x3cc8bdfb,0xbde2bd71,0x3dffbc49,0xbd443ded,0xbdd53d8e,0x3d153df5,0xbdc6bda2,0x3dedbd44,0x3dfb3cc8,0x3d71bde2,0x3c493dff,
0x3d803d80,0xbd44bded,0xbdfb3cc8,0x3dd5bd8e,0x3db5bdb5,0xbded3d44,0x3cc83dfb,0xbd8ebdd5,0xbdb5bdb5,0x3d443ded,0x3dfbbcc8,0xbdd53d8e,0xbdb53db5,0x3dedbd44,0xbcc8bdfb,0x3d8e3dd5,
0xbd803d80,0x3cc83dfb,0x3dffbc49,0xbdf53d15,0x3ded3d44,0x3dd53d8e,0x3da2bdc6,0xbd713de2,0x3dedbd44,0x3dfbbcc8,0xbc49bdff,0x3d153df5,0x3d44bded,0x3d8ebdd5,0xbdc6bda2,0x3de23d71,
0x3d803d80,0xbe00,0xbe000000,0x3e000000,0x3e00,0xbe00,0xbe000000,0x3e000000,0x3e00,0xbe00,0xbe000000,0x3e000000,0x3e00,0xbe00,0xbe000000,0x3e000000,
0xbd803d80,0xbcc83dfb,0x3dff3c49,0xbdf5bd15,0xbded3d44,0xbdd53d8e,0x3da23dc6,0xbd71bde2,0xbdedbd44,0xbdfbbcc8,0xbc493dff,0x3d15bdf5,0xbd44bded,0xbd8ebdd5,0xbdc63da2,0x3de2bd71,
0x3d803d80,0x3d44bded,0xbdfbbcc8,0x3dd53d8e,0xbdb5bdb5,0x3ded3d44,0x3cc8bdfb,0xbd8e3dd5,0x3db5bdb5,0xbd443ded,0x3dfb3cc8,0xbdd5bd8e,0x3db53db5,0xbdedbd44,0xbcc83dfb,0x3d8ebdd5,
0xbd803d80,0xbd8e3dd5,0x3df53d15,0xbda2bdc6,0x3d44bded,0xbcc8bdfb,0xbde23d71,0x3dff3c49,0x3d443ded,0x3dd53d8e,0x3d15bdf5,0xbdc63da2,0xbdedbd44,0xbdfb3cc8,0x3d713de2,0x3c49bdff,
0x3d803d80,0x3db5bdb5,0xbdedbd44,0x3d443ded,0x3e000000,0xbdb53db5,0x3ded3d44,0xbd44bded,0xbe000000,0x3db5bdb5,0xbdedbd44,0x3d443ded,0x3e000000,0xbdb53db5,0x3ded3d44,0xbd44bded,
0xbd803d80,0xbdd53d8e,0x3de23d71,0xbc49bdff,0x3d443ded,0x3dfb3cc8,0xbd15bdf5,0xbda23dc6,0x3d44bded,0xbd8ebdd5,0xbd713de2,0x3dffbc49,0xbded3d44,0xbcc83dfb,0x3df5bd15,0xbdc6bda2,
0x3d803d80,0x3dedbd44,0xbdd5bd8e,0xbcc83dfb,0xbdb53db5,0xbd44bded,0xbd8e3dd5,0x3dfb3cc8,0x3db53db5,0xbded3d44,0x3dd53d8e,0x3cc8bdfb,0x3db5bdb5,0x3d443ded,0x3d8ebdd5,0xbdfbbcc8,
0xbd803d80,0xbdfb3cc8,0x3dc63da2,0x3d71bde2,0xbdedbd44,0xbd8e3dd5,0x3dffbc49,0xbd15bdf5,0xbded3d44,0x3cc83dfb,0x3da2bdc6,0xbde2bd71,0xbd443ded,0x3dd53d8e,0xbc49bdff,0xbdf53d15,
0x3d803d80,0x3e000000,0xbdb5bdb5,0xbdb53db5,0xbe00,0x3e000000,0xbdb5bdb5,0xbdb53db5,0xbe00,0x3e000000,0xbdb5bdb5,0xbdb53db5,0xbe00,0x3e000000,0xbdb5bdb5,0xbdb53db5,
0xbd803d80,0xbdfbbcc8,0x3da23dc6,0x3de2bd71,0x3dedbd44,0xbd8ebdd5,0xbc493dff,0x3df53d15,0x3ded3d44,0x3cc8bdfb,0xbdc63da2,0x3d713de2,0x3d443ded,0x3dd5bd8e,0xbdffbc49,0xbd153df5,
0x3d803d80,0x3ded3d44,0xbd8ebdd5,0xbdfb3cc8,0x3db53db5,0xbd443ded,0x3dd5bd8e,0xbcc8bdfb,0xbdb53db5,0xbdedbd44,0x3d8e3dd5,0x3dfbbcc8,0xbdb5bdb5,0x3d44bded,0xbdd53d8e,0x3cc83dfb,
0xbd803d80,0xbdd5bd8e,0x3d713de2,0x3dff3c49,0xbd443ded,0x3dfbbcc8,0xbdf5bd15,0xbdc63da2,0xbd44bded,0xbd8e3dd5,0x3de2bd71,0x3c49bdff,0x3ded3d44,0xbcc8bdfb,0xbd153df5,0x3da23dc6,
0x3d803d80,0x3db53db5,0xbd44bded,0xbdedbd44,0xbe000000,0xbdb5bdb5,0x3d443ded,0x3ded3d44,0x3e000000,0x3db53db5,0xbd44bded,0xbdedbd44,0xbe000000,0xbdb5bdb5,0x3d443ded,0x3ded3d44,
0xbd803d80,0xbd8ebdd5,0x3d153df5,0x3dc63da2,0xbd44bded,0xbcc83dfb,0x3d71bde2,0xbc49bdff,0xbd443ded,0x3dd5bd8e,0xbdf53d15,0xbda23dc6,0x3dedbd44,0xbdfbbcc8,0x3de23d71,0x3dffbc49,
0x3d803d80,0x3d443ded,0xbcc8bdfb,0xbd8ebdd5,0x3db5bdb5,0x3dedbd44,0xbdfb3cc8,0xbdd53d8e,0xbdb5bdb5,0xbd44bded,0x3cc83dfb,0x3d8e3dd5,0xbdb53db5,0xbded3d44,0x3dfbbcc8,0x3dd5bd8e,
0xbd803d80,0xbcc8bdfb,0x3c493dff,0x3d153df5,0x3ded3d44,0xbdd5bd8e,0x3dc63da2,0x3de23d71,0x3dedbd44,0xbdfb3cc8,0x3dffbc49,0x3df5bd15,0x3d44bded,0xbd8e3dd5,0x3da2bdc6,0x3d71bde2,
0xbc493dff,0xbbc93e00,0xbb493e00,0xbc173dff,0xbcc83dfb,0xbcf93df8,0xbce03dfa,0xbd093df7,0xbd443ded,0xbd5b3de7,0xbd4f3dea,0xbd663de5,0xbd8e3dd5,0xbd983dce,0xbd933dd1,0xbd9d3dca,
0xbd713de2,0xbcf93df8,0xbc7b3dfe,0xbd383def,0xbdd53d8e,0xbdf13d2c,0xbde53d66,0xbdfa3ce0,0xbdedbd44,0xbdcebd98,0xbddfbd7c,0xbdb9bdb1,0xbcc8bdfb,0x3bc9be00,0xbc17bdff,0x3cafbdfc,
0xbdc63da2,0xbd5b3de7,0xbce03dfa,0xbd9d3dca,0xbdfbbcc8,0xbdcebd98,0xbdeabd4f,0xbda7bdc2,0x3d44bded,0x3dbebdac,0x3d93bdd1,0x3ddfbd7c,0x3dd53d8e,0x3d843ddc,0x3db13db9,0x3d213df3,
0xbdf53d15,0xbd983dce,0xbd213df3,0xbdd13d93,0xbd8ebdd5,0x3bc9be00,0xbd09bdf7,0x3d38bdef,0x3ded3d44,0x3d843ddc,0x3dc23da7,0x3ce03dfa,0xbdfb3cc8,0xbde7bd5b,0xbdfebc7b,0xbdb9bdb1,
0xbdffbc49,0xbdbe3dac,0xbd4f3dea,0xbdf33d21,0x3cc8bdfb,0x3ddcbd84,0x3d93bdd1,0x3dfebc7b,0xbd443ded,0xbdf13d2c,0xbdb93db1,0xbdffbc17,0x3d8ebdd5,0x3dfdbc96,0x3dd8bd89,0x3df73d09,
0xbde2bd71,0xbddc3d84,0xbd7c3ddf,0xbe003b49,0x3dd5bd8e,0x3de73d5b,0x3dffbc17,0x3d933dd1,0xbdedbd44,0xbc96bdfd,0xbd9dbdca,0x3d38bdef,0x3cc83dfb,0xbdbe3dac,0xbd213df3,0xbdfa3ce0,
0xbda2bdc6,0xbdf13d2c,0xbd933dd1,0xbdf7bd09,0x3dfb3cc8,0x3c963dfd,0x3db13db9,0xbd663de5,0x3d44bded,0x3e003bc9,0x3dd8bd89,0x3dca3d9d,0xbdd5bd8e,0x3cf9bdf8,0xbd38bdef,0x3dc2bda7,
0xbd15bdf5,0xbdfd3c96,0xbda73dc2,0xbdd8bd89,0x3d8e3dd5,0xbdbe3dac,0xbc7b3dfe,0xbe003b49,0x3ded3d44,0xbcf93df8,0x3d663de5,0xbdd13d93,0x3dfbbcc8,0x3d2c3df1,0x3ddf3d7c,0xbd383def,
0x3c49bdff,0xbe00bbc9,0xbdb93db1,0xbda7bdc2,0xbcc83dfb,0xbdf8bcf9,0xbdd83d89,0xbd7cbddf,0xbd443ded,0xbde7bd5b,0xbdef3d38,0xbd21bdf3,0xbd8e3dd5,0xbdcebd98,0xbdfc3caf,0xbc7bbdfe,
0x3d71bde2,0xbdf8bcf9,0xbdca3d9d,0xbd4fbdea,0xbdd53d8e,0xbd2cbdf1,0xbdf3bd21,0x3d89bdd8,0xbdedbd44,0x3d98bdce,0xbd09bdf7,0x3e00bb49,0xbcc8bdfb,0x3e003bc9,0x3da7bdc2,0x3d933dd1,
0x3dc6bda2,0xbde7bd5b,0xbdd83d89,0xbc7bbdfe,0xbdfbbcc8,0x3d98bdce,0xbd38bdef,0x3dff3c17,0x3d44bded,0x3dac3dbe,0x3dfcbcaf,0xbd093df7,0x3dd53d8e,0xbddc3d84,0xbb493e00,0xbde5bd66,
0x3df5bd15,0xbdcebd98,0xbde53d66,0x3cafbdfc,0xbd8ebdd5,0x3e003bc9,0x3d7cbddf,0x3d4f3dea,0x3ded3d44,0xbddc3d84,0x3c173dff,0xbdd8bd89,0xbdfb3cc8,0x3d5bbde7,0xbd9dbdca,0x3e00bb49,
0x3dff3c49,0xbdacbdbe,0xbdef3d38,0x3d66bde5,0x3cc8bdfb,0x3d843ddc,0x3dfcbcaf,0xbd9d3dca,0xbd443ded,0xbd2cbdf1,0xbe00bb49,0x3dc2bda7,0x3d8ebdd5,0x3c963dfd,0x3dfa3ce0,0xbddf3d7c,
0x3de23d71,0xbd84bddc,0xbdf73d09,0x3db1bdb9,0x3dd5bd8e,0xbd5b3de7,0x3dc23da7,0xbdfcbcaf,0xbdedbd44,0x3dfdbc96,0x3c7bbdfe,0x3d4f3dea,0x3cc83dfb,0xbdacbdbe,0xbde53d66,0x3d89bdd8,
0x3da23dc6,0xbd2cbdf1,0xbdfc3caf,0x3ddfbd7c,0x3dfb3cc8,0xbdfd3c96,0xbb493e00,0xbd21bdf3,0x3d44bded,0xbbc93e00,0x3dfa3ce0,0xbdfe3c7b,0xbdd5bd8e,0x3df83cf9,0x3d4fbdea,0xbc173dff,
0x3d153df5,0xbc96bdfd,0xbdff3c17,0x3dfabce0,0x3d8e3dd5,0xbdacbdbe,0xbdca3d9d,0x3db1bdb9,0x3ded3d44,0xbdf8bcf9,0xbd213df3,0x3cafbdfc,0x3dfbbcc8,0xbdf13d2c,0x3d093df7,0xbd4fbdea,
0xbc493dff,0x3bc9be00,0xbe00bb49,0x3dff3c17,0xbcc83dfb,0x3cf9bdf8,0xbdfabce0,0x3df73d09,0xbd443ded,0x3d5bbde7,0xbdeabd4f,0x3de53d66,0xbd8e3dd5,0x3d98bdce,0xbdd1bd93,0x3dca3d9d,
0xbd713de2,0x3cf9bdf8,0xbdfebc7b,0x3def3d38,0xbdd53d8e,0x3df1bd2c,0xbd66bde5,0x3ce03dfa,0xbdedbd44,0x3dce3d98,0x3d7cbddf,0xbdb13db9,0xbcc8bdfb,0xbbc93e00,0x3dffbc17,0xbdfcbcaf,
0xbdc63da2,0x3d5bbde7,0xbdfabce0,0x3dca3d9d,0xbdfbbcc8,0x3dce3d98,0x3d4fbdea,0xbdc23da7,0x3d44bded,0xbdbe3dac,0x3dd13d93,0xbd7cbddf,0x3dd53d8e,0xbd84bddc,0xbdb93db1,0x3df3bd21,
0xbdf53d15,0x3d98bdce,0xbdf3bd21,0x3d933dd1,0xbd8ebdd5,0xbbc93e00,0x3df7bd09,0xbdefbd38,0x3ded3d44,0xbd84bddc,0xbda73dc2,0x3dfabce0,0xbdfb3cc8,0x3de73d5b,0x3c7bbdfe,0xbdb13db9,
0xbdffbc49,0x3dbebdac,0xbdeabd4f,0x3d213df3,0x3cc8bdfb,0xbddc3d84,0x3dd13d93,0xbc7bbdfe,0xbd443ded,0x3df1bd2c,0xbdb1bdb9,0xbc173dff,0x3d8ebdd5,0xbdfd3c96,0x3d893dd8,0x3d09bdf7,
0xbde2bd71,0x3ddcbd84,0xbddfbd7c,0x3b493e00,0x3dd5bd8e,0xbde7bd5b,0x3c173dff,0x3dd1bd93,0xbdedbd44,0x3c963dfd,0x3dcabd9d,0xbdefbd38,0x3cc83dfb,0x3dbebdac,0xbdf3bd21,0x3ce03dfa,
0xbda2bdc6,0x3df1bd2c,0xbdd1bd93,0xbd093df7,0x3dfb3cc8,0xbc96bdfd,0xbdb93db1,0x3de53d66,0x3d44bded,0xbe00bbc9,0x3d893dd8,0x3d9dbdca,0xbdd5bd8e,0xbcf93df8,0x3defbd38,0xbda7bdc2,
0xbd15bdf5,0x3dfdbc96,0xbdc2bda7,0xbd893dd8,0x3d8e3dd5,0x3dbebdac,0xbdfebc7b,0x3b493e00,0x3ded3d44,0x3cf9bdf8,0xbde53d66,0x3d933dd1,0x3dfbbcc8,0xbd2cbdf1,0xbd7c3ddf,0x3def3d38,
0x3c49bdff,0x3e003bc9,0xbdb1bdb9,0xbdc23da7,0xbcc83dfb,0x3df83cf9,0xbd89bdd8,0xbddf3d7c,0xbd443ded,0x3de73d5b,0xbd38bdef,0xbdf33d21,0xbd8e3dd5,0x3dce3d98,0xbcafbdfc,0xbdfe3c7b,
0x3d71bde2,0x3df83cf9,0xbd9dbdca,0xbdea3d4f,0xbdd53d8e,0x3d2c3df1,0x3d21bdf3,0xbdd8bd89,0xbdedbd44,0xbd983dce,0x3df7bd09,0xbb49be00,0xbcc8bdfb,0xbe00bbc9,0x3dc23da7,0x3dd1bd93,
0x3dc6bda2,0x3de73d5b,0xbd89bdd8,0xbdfe3c7b,0xbdfbbcc8,0xbd983dce,0x3defbd38,0x3c17bdff,0x3d44bded,0xbdacbdbe,0x3caf3dfc,0x3df73d09,0x3dd53d8e,0x3ddcbd84,0xbe00bb49,0xbd663de5,
0x3df5bd15,0x3dce3d98,0xbd66bde5,0xbdfcbcaf,0xbd8ebdd5,0xbe00bbc9,0x3ddf3d7c,0x3deabd4f,0x3ded3d44,0x3ddcbd84,0xbdff3c17,0xbd893dd8,0xbdfb3cc8,0xbd5b3de7,0x3dcabd9d,0xbb49be00,
0x3dff3c49,0x3dac3dbe,0xbd38bdef,0xbde5bd66,0x3cc8bdfb,0xbd84bddc,0x3caf3dfc,0x3dca3d9d,0xbd443ded,0x3d2c3df1,0x3b49be00,0xbda7bdc2,0x3d8ebdd5,0xbc96bdfd,0xbce03dfa,0x3d7c3ddf,
0x3de23d71,0x3d843ddc,0xbd09bdf7,0xbdb9bdb1,0x3dd5bd8e,0x3d5bbde7,0xbda73dc2,0xbcaf3dfc,0xbdedbd44,0xbdfd3c96,0x3dfe3c7b,0x3deabd4f,0x3cc83dfb,0x3dac3dbe,0xbd66bde5,0xbdd8bd89,
0x3da23dc6,0x3d2c3df1,0xbcafbdfc,0xbd7cbddf,0x3dfb3cc8,0x3dfdbc96,0xbe00bb49,0xbdf33d21,0x3d44bded,0x3bc9be00,0xbce03dfa,0x3c7b3dfe,0xbdd5bd8e,0xbdf8bcf9,0x3dea3d4f,0x3dff3c17,
0x3d153df5,0x3c963dfd,0xbc17bdff,0xbce0bdfa,0x3d8e3dd5,0x3dac3dbe,0xbd9dbdca,0xbdb9bdb1,0x3ded3d44,0x3df83cf9,0xbdf3bd21,0xbdfcbcaf,0x3dfbbcc8,0x3df1bd2c,0xbdf73d09,0xbdea3d4f,
0xbdb53d80,0xbdbe3dac,0xbdb93db1,0xbdc23da7,0xbd153df5,0xbddc3d84,0xbdd83d89,0xbddf3d7c,0xbd713de2,0xbdf13d2c,0xbdef3d38,0xbdf33d21,0xbda23dc6,0xbdfd3c96,0xbdfc3caf,0xbdfe3c7b,
0x3db53d80,0x3ddcbd84,0x3dcabd9d,0x3deabd4f,0xbdff3c49,0x3de73d5b,0x3df33d21,0x3dd83d89,0xbda2bdc6,0x3c963dfd,0x3d093df7,0x3b493e00,0x3d15bdf5,0xbdbe3dac,0xbda73dc2,0xbdd13d93,
0xbdb53d80,0xbdf13d2c,0xbdd83d89,0xbdfe3c7b,0xbd71bde2,0xbc96bdfd,0xbd38bdef,0x3c17bdff,0x3df5bd15,0x3e003bc9,0x3dfcbcaf,0x3df73d09,0x3c493dff,0xbcf93df8,0xbb493e00,0xbd663de5,
0x3db53d80,0x3dfdbc96,0x3de5bd66,0x3dfc3caf,0x3da2bdc6,0xbdbe3dac,0xbd7c3ddf,0xbdea3d4f,0xbc493dff,0x3cf9bdf8,0xbc17bdff,0x3d89bdd8,0xbd71bde2,0x3d2c3df1,0x3d9d3dca,0x3b493e00,
0xbdb53d80,0xbe00bbc9,0xbdef3d38,0xbde5bd66,0x3df53d15,0x3df83cf9,0x3dfcbcaf,0x3dca3d9d,0xbde2bd71,0xbde7bd5b,0xbe00bb49,0xbda7bdc2,0x3dc63da2,0x3dce3d98,0x3dfa3ce0,0x3d7c3ddf,
0x3db53d80,0x3df83cf9,0x3df7bd09,0x3db93db1,0x3c493dff,0xbd2cbdf1,0xbdc2bda7,0x3cafbdfc,0x3dc6bda2,0xbd983dce,0xbc7b3dfe,0xbdea3d4f,0xbdf5bd15,0x3e003bc9,0x3de5bd66,0x3dd83d89,
0xbdb53d80,0xbde7bd5b,0xbdfc3caf,0xbd7cbddf,0xbde23d71,0xbd983dce,0xbb493e00,0xbdf33d21,0x3d153df5,0x3dac3dbe,0x3dfa3ce0,0x3c7b3dfe,0x3dffbc49,0x3ddcbd84,0x3d4fbdea,0x3dff3c17,
0x3db53d80,0x3dce3d98,0x3dffbc17,0x3ce03dfa,0xbdc6bda2,0x3e003bc9,0x3dcabd9d,0x3db93db1,0xbdffbc49,0x3ddcbd84,0x3d21bdf3,0x3dfc3caf,0xbde23d71,0x3d5bbde7,0xbd09bdf7,0x3deabd4f,
0xbdb53d80,0xbdacbdbe,0xbe00bb49,0x3c17bdff,0x3d15bdf5,0xbd84bddc,0xbdfabce0,0x3d09bdf7,0x3d71bde2,0xbd2cbdf1,0xbdeabd4f,0x3d66bde5,0x3da2bdc6,0xbc96bdfd,0xbdd1bd93,0x3d9dbdca,
0x3db53d80,0x3d843ddc,0x3dfe3c7b,0xbd383def,0x3dffbc49,0xbd5b3de7,0x3d663de5,0xbdfa3ce0,0x3da23dc6,0xbdfd3c96,0xbd7c3ddf,0xbdb9bdb1,0xbd153df5,0xbdacbdbe,0xbdff3c17,0x3cafbdfc,
0xbdb53d80,0xbd2cbdf1,0xbdfabce0,0x3d9dbdca,0x3d713de2,0x3dfdbc96,0x3d4fbdea,0x3da73dc2,0xbdf53d15,0xbbc93e00,0x3dd13d93,0xbddf3d7c,0xbc49bdff,0xbdf8bcf9,0xbdb93db1,0xbd21bdf3,
0x3db53d80,0x3c963dfd,0x3df33d21,0xbdd13d93,0xbda23dc6,0xbdacbdbe,0xbdf73d09,0x3d38bdef,0x3c49bdff,0x3df83cf9,0x3da7bdc2,0x3ce03dfa,0x3d713de2,0xbdf13d2c,0xbc7b3dfe,0xbdb9bdb1,
0xbdb53d80,0x3bc9be00,0xbdeabd4f,0x3df3bd21,0xbdf5bd15,0xbcf93df8,0x3dd13d93,0xbdfe3c7b,0x3de23d71,0x3d5bbde7,0xbdb1bdb9,0x3dff3c17,0xbdc6bda2,0xbd983dce,0x3d893dd8,0xbdf7bd09,
0x3db53d80,0xbcf93df8,0x3ddf3d7c,0xbe003b49,0xbc49bdff,0x3df1bd2c,0xbc17bdff,0x3d933dd1,0xbdc63da2,0xbdcebd98,0xbdca3d9d,0x3d38bdef,0x3df53d15,0xbbc93e00,0x3df33d21,0xbdfa3ce0,
0xbdb53d80,0x3d5bbde7,0xbdd1bd93,0x3df73d09,0x3de2bd71,0xbdcebd98,0xbdb93db1,0x3d66bde5,0xbd15bdf5,0xbdbe3dac,0x3d893dd8,0xbdcabd9d,0xbdff3c49,0x3d843ddc,0x3defbd38,0xbdc23da7,
0x3db53d80,0xbd983dce,0x3dc23da7,0xbdd8bd89,0x3dc63da2,0xbbc93e00,0x3dfe3c7b,0xbe003b49,0x3dff3c49,0x3d843ddc,0x3de5bd66,0xbdd13d93,0x3de2bd71,0x3de73d5b,0x3d7cbddf,0xbd383def,
0xbdb53d80,0x3dbebdac,0xbdb1bdb9,0x3da73dc2,0xbd153df5,0x3ddcbd84,0xbd89bdd8,0x3d7c3ddf,0xbd713de2,0x3df1bd2c,0xbd38bdef,0x3d213df3,0xbda23dc6,0x3dfdbc96,0xbcafbdfc,0x3c7b3dfe,
0x3db53d80,0xbddc3d84,0x3d9d3dca,0xbd4fbdea,0xbdff3c49,0xbde7bd5b,0xbd213df3,0x3d89bdd8,0xbda2bdc6,0xbc96bdfd,0xbdf73d09,0x3e00bb49,0x3d15bdf5,0x3dbebdac,0xbdc2bda7,0x3d933dd1,
0xbdb53d80,0x3df1bd2c,0xbd89bdd8,0x3c7b3dfe,0xbd71bde2,0x3c963dfd,0x3defbd38,0xbdffbc17,0x3df5bd15,0xbe00bbc9,0x3caf3dfc,0x3d09bdf7,0x3c493dff,0x3cf9bdf8,0xbe00bb49,0x3de53d66,
0x3db53d80,0xbdfd3c96,0x3d663de5,0x3cafbdfc,0x3da2bdc6,0x3dbebdac,0xbddfbd7c,0x3d4f3dea,0xbc493dff,0xbcf93df8,0x3dffbc17,0xbdd8bd89,0xbd71bde2,0xbd2cbdf1,0xbdca3d9d,0x3e00bb49,
0xbdb53d80,0x3e003bc9,0xbd38bdef,0xbd663de5,0x3df53d15,0xbdf8bcf9,0x3caf3dfc,0x3d9dbdca,0xbde2bd71,0x3de73d5b,0x3b49be00,0xbdc23da7,0x3dc63da2,0xbdcebd98,0xbce03dfa,0x3ddfbd7c,
0x3db53d80,0xbdf8bcf9,0x3d093df7,0x3db1bdb9,0x3c493dff,0x3d2c3df1,0x3da7bdc2,0xbdfcbcaf,0x3dc6bda2,0x3d98bdce,0xbdfebc7b,0x3d4f3dea,0xbdf5bd15,0xbe00bbc9,0x3d663de5,0x3d89bdd8,
0xbdb53d80,0x3de73d5b,0xbcafbdfc,0xbddf3d7c,0xbde23d71,0x3d98bdce,0xbe00bb49,0x3d213df3,0x3d153df5,0xbdacbdbe,0xbce03dfa,0x3dfebc7b,0x3dffbc49,0xbddc3d84,0x3dea3d4f,0x3c17bdff,
0x3db53d80,0xbdcebd98,0x3c173dff,0x3dfabce0,0xbdc6bda2,0xbe00bbc9,0x3d9d3dca,0x3db1bdb9,0xbdffbc49,0xbddc3d84,0x3df33d21,0x3cafbdfc,0xbde23d71,0xbd5b3de7,0x3df7bd09,0xbd4fbdea,
0xbdb53d80,0x3dac3dbe,0x3b49be00,0xbdffbc17,0x3d15bdf5,0x3d843ddc,0x3ce0bdfa,0xbdf7bd09,0x3d71bde2,0x3d2c3df1,0x3d4fbdea,0xbde5bd66,0x3da2bdc6,0x3c963dfd,0x3d93bdd1,0xbdcabd9d,
0x3db53d80,0xbd84bddc,0xbc7b3dfe,0x3def3d38,0x3dffbc49,0x3d5bbde7,0xbde53d66,0x3ce03dfa,0x3da23dc6,0x3dfdbc96,0xbddfbd7c,0xbdb13db9,0xbd153df5,0x3dac3dbe,0xbc17bdff,0xbdfcbcaf,
0xbdb53d80,0x3d2c3df1,0x3ce0bdfa,0xbdcabd9d,0x3d713de2,0xbdfd3c96,0x3dea3d4f,0x3dc2bda7,0xbdf53d15,0x3bc9be00,0xbd933dd1,0x3d7c3ddf,0xbc49bdff,0x3df83cf9,0xbdb1bdb9,0xbdf33d21,
0x3db53d80,0xbc96bdfd,0xbd213df3,0x3d933dd1,0xbda23dc6,0x3dac3dbe,0xbd09bdf7,0xbdefbd38,0x3c49bdff,0xbdf8bcf9,0x3dc23da7,0x3dfabce0,0x3d713de2,0x3df1bd2c,0xbdfebc7b,0xbdb13db9,
0xbdb53d80,0xbbc93e00,0x3d4fbdea,0xbd21bdf3,0xbdf5bd15,0x3cf9bdf8,0xbd933dd1,0x3c7b3dfe,0x3de23d71,0xbd5b3de7,0x3db9bdb1,0x3c17bdff,0xbdc6bda2,0x3d98bdce,0xbdd83d89,0xbd093df7,
0x3db53d80,0x3cf9bdf8,0xbd7c3ddf,0x3b493e00,0xbc49bdff,0xbdf13d2c,0x3dffbc17,0x3dd1bd93,0xbdc63da2,0x3dce3d98,0xbd9dbdca,0xbdefbd38,0x3df53d15,0x3bc9be00,0xbd213df3,0x3ce03dfa,
0xbdb53d80,0xbd5b3de7,0x3d93bdd1,0x3d09bdf7,0x3de2bd71,0x3dce3d98,0xbdb1bdb9,0xbde5bd66,0xbd15bdf5,0x3dbebdac,0xbdd83d89,0xbd9d3dca,0xbdff3c49,0xbd84bddc,0x3d383def,0x3da73dc2,
0x3db53d80,0x3d98bdce,0xbda73dc2,0xbd893dd8,0x3dc63da2,0x3bc9be00,0xbc7b3dfe,0x3b493e00,0x3dff3c49,0xbd84bddc,0x3d663de5,0x3d933dd1,0x3de2bd71,0xbde7bd5b,0x3ddf3d7c,0x3def3d38,
0xbcc83dfb,0xbc493dff,0xbbc93e00,0xbc963dfd,0xbd443ded,0xbd713de2,0xbd5b3de7,0xbd843ddc,0xbdb53db5,0xbdc63da2,0xbdbe3dac,0xbdce3d98,0xbded3d44,0xbdf53d15,0xbdf13d2c,0xbdf83cf9,
0xbd8e3dd5,0xbd153df5,0xbc963dfd,0xbd5b3de7,0xbded3d44,0xbdff3c49,0xbdf83cf9,0xbe00bbc9,0xbdb5bdb5,0xbd71bde2,0xbd98bdce,0xbd2cbdf1,0x3d44bded,0x3da2bdc6,0x3d84bddc,0x3dbebdac,
0xbdd53d8e,0xbd713de2,0xbcf93df8,0xbdac3dbe,0xbdedbd44,0xbda2bdc6,0xbdcebd98,0xbd5bbde7,0x3db5bdb5,0x3df5bd15,0x3ddcbd84,0x3e00bbc9,0x3d443ded,0xbc493dff,0x3c963dfd,0xbd2c3df1,
0xbdfb3cc8,0xbda23dc6,0xbd2c3df1,0xbddc3d84,0xbd44bded,0x3d15bdf5,0xbbc9be00,0x3d98bdce,0x3db53db5,0x3c493dff,0x3d5b3de7,0xbcf93df8,0xbdedbd44,0xbd71bde2,0xbdbebdac,0xbc96bdfd,
0xbdfbbcc8,0xbdc63da2,0xbd5b3de7,0xbdf83cf9,0x3d44bded,0x3df5bd15,0x3dbebdac,0x3dfd3c96,0xbdb53db5,0xbdffbc49,0xbdf13d2c,0xbddcbd84,0x3dedbd44,0x3de23d71,0x3e003bc9,0x3d983dce,
0xbdd5bd8e,0xbde23d71,0xbd843ddc,0xbe00bbc9,0x3dedbd44,0x3dc63da2,0x3dfd3c96,0x3d2c3df1,0xbdb5bdb5,0x3d15bdf5,0xbcf9bdf8,0x3dbebdac,0xbd443ded,0xbdff3c49,0xbdce3d98,0xbde7bd5b,
0xbd8ebdd5,0xbdf53d15,0xbd983dce,0xbdf1bd2c,0x3ded3d44,0xbc493dff,0x3d843ddc,0xbdac3dbe,0x3db5bdb5,0x3de23d71,0x3dfdbc96,0x3d5b3de7,0xbd44bded,0x3dc6bda2,0x3cf9bdf8,0x3e00bbc9,
0xbcc8bdfb,0xbdff3c49,0xbdac3dbe,0xbdcebd98,0x3d443ded,0xbde23d71,0xbd2c3df1,0xbdf8bcf9,0x3db53db5,0xbda23dc6,0x3bc93e00,0xbdfd3c96,0x3ded3d44,0xbd153df5,0x3d5b3de7,0xbddc3d84,
0x3cc8bdfb,0xbdffbc49,0xbdbe3dac,0xbd98bdce,0xbd443ded,0xbde2bd71,0xbdf13d2c,0xbcf9bdf8,0xbdb53db5,0xbda2bdc6,0xbe00bbc9,0x3c96bdfd,0xbded3d44,0xbd15bdf5,0xbde7bd5b,0x3d84bddc,
0x3d8ebdd5,0xbdf5bd15,0xbdce3d98,0xbd2cbdf1,0xbded3d44,0xbc49bdff,0xbddcbd84,0x3dbebdac,0xbdb5bdb5,0x3de2bd71,0x3c96bdfd,0x3de73d5b,0x3d44bded,0x3dc63da2,0x3df8bcf9,0xbbc93e00,
0x3dd5bd8e,0xbde2bd71,0xbddc3d84,0xbbc9be00,0xbdedbd44,0x3dc6bda2,0xbc96bdfd,0x3df13d2c,0x3db5bdb5,0x3d153df5,0x3df83cf9,0xbdac3dbe,0x3d443ded,0xbdffbc49,0xbd983dce,0xbd5bbde7,
0x3dfbbcc8,0xbdc6bda2,0xbde73d5b,0x3cf9bdf8,0xbd44bded,0x3df53d15,0x3dacbdbe,0x3c963dfd,0x3db53db5,0xbdff3c49,0xbd2c3df1,0xbd84bddc,0xbdedbd44,0x3de2bd71,0xbbc9be00,0x3dce3d98,
0x3dfb3cc8,0xbda2bdc6,0xbdf13d2c,0x3d84bddc,0x3d44bded,0x3d153df5,0x3e003bc9,0xbdce3d98,0xbdb53db5,0x3c49bdff,0xbde7bd5b,0x3df8bcf9,0x3dedbd44,0xbd713de2,0x3dac3dbe,0xbdfdbc96,
0x3dd53d8e,0xbd71bde2,0xbdf83cf9,0x3dbebdac,0x3dedbd44,0xbda23dc6,0x3d983dce,0xbde7bd5b,0xbdb5bdb5,0x3df53d15,0x3d84bddc,0xbbc93e00,0xbd443ded,0xbc49bdff,0xbdfdbc96,0x3df1bd2c,
0x3d8e3dd5,0xbd15bdf5,0xbdfd3c96,0x3de7bd5b,0x3ded3d44,0xbdffbc49,0xbcf93df8,0xbbc9be00,0x3db5bdb5,0xbd713de2,0x3dce3d98,0xbdf1bd2c,0xbd44bded,0x3da23dc6,0x3ddcbd84,0xbdac3dbe,
0x3cc83dfb,0xbc49bdff,0xbe003bc9,0x3dfdbc96,0x3d443ded,0xbd71bde2,0xbde73d5b,0x3ddcbd84,0x3db53db5,0xbdc6bda2,0xbdac3dbe,0x3d98bdce,0x3ded3d44,0xbdf5bd15,0xbd2c3df1,0x3cf9bdf8,
0xbcc83dfb,0x3c49bdff,0xbe00bbc9,0x3dfd3c96,0xbd443ded,0x3d71bde2,0xbde7bd5b,0x3ddc3d84,0xbdb53db5,0x3dc6bda2,0xbdacbdbe,0x3d983dce,0xbded3d44,0x3df5bd15,0xbd2cbdf1,0x3cf93df8,
0xbd8e3dd5,0x3d15bdf5,0xbdfdbc96,0x3de73d5b,0xbded3d44,0x3dffbc49,0xbcf9bdf8,0xbbc93e00,0xbdb5bdb5,0x3d713de2,0x3dcebd98,0xbdf13d2c,0x3d44bded,0xbda23dc6,0x3ddc3d84,0xbdacbdbe,
0xbdd53d8e,0x3d71bde2,0xbdf8bcf9,0x3dbe3dac,0xbdedbd44,0x3da23dc6,0x3d98bdce,0xbde73d5b,0x3db5bdb5,0xbdf53d15,0x3d843ddc,0xbbc9be00,0x3d443ded,0x3c49bdff,0xbdfd3c96,0x3df13d2c,
0xbdfb3cc8,0x3da2bdc6,0xbdf1bd2c,0x3d843ddc,0xbd44bded,0xbd153df5,0x3e00bbc9,0xbdcebd98,0x3db53db5,0xbc49bdff,0xbde73d5b,0x3df83cf9,0xbdedbd44,0x3d713de2,0x3dacbdbe,0xbdfd3c96,
0xbdfbbcc8,0x3dc6bda2,0xbde7bd5b,0x3cf93df8,0x3d44bded,0xbdf53d15,0x3dac3dbe,0x3c96bdfd,0xbdb53db5,0x3dff3c49,0xbd2cbdf1,0xbd843ddc,0x3dedbd44,0xbde2bd71,0xbbc93e00,0x3dcebd98,
0xbdd5bd8e,0x3de2bd71,0xbddcbd84,0xbbc93e00,0x3dedbd44,0xbdc6bda2,0xbc963dfd,0x3df1bd2c,0xbdb5bdb5,0xbd153df5,0x3df8bcf9,0xbdacbdbe,0xbd443ded,0x3dffbc49,0xbd98bdce,0xbd5b3de7,
0xbd8ebdd5,0x3df5bd15,0xbdcebd98,0xbd2c3df1,0x3ded3d44,0x3c49bdff,0xbddc3d84,0x3dbe3dac,0x3db5bdb5,0xbde2bd71,0x3c963dfd,0x3de7bd5b,0xbd44bded,0xbdc63da2,0x3df83cf9,0xbbc9be00,
0xbcc8bdfb,0x3dffbc49,0xbdbebdac,0xbd983dce,0x3d443ded,0x3de2bd71,0xbdf1bd2c,0xbcf93df8,0x3db53db5,0x3da2bdc6,0xbe003bc9,0x3c963dfd,0x3ded3d44,0x3d15bdf5,0xbde73d5b,0x3d843ddc,
0x3cc8bdfb,0x3dff3c49,0xbdacbdbe,0xbdce3d98,0xbd443ded,0x3de23d71,0xbd2cbdf1,0xbdf83cf9,0xbdb53db5,0x3da23dc6,0x3bc9be00,0xbdfdbc96,0xbded3d44,0x3d153df5,0x3d5bbde7,0xbddcbd84,
0x3d8ebdd5,0x3df53d15,0xbd98bdce,0xbdf13d2c,0xbded3d44,0x3c493dff,0x3d84bddc,0xbdacbdbe,0xbdb5bdb5,0xbde23d71,0x3dfd3c96,0x3d5bbde7,0x3d44bded,0xbdc6bda2,0x3cf93df8,0x3e003bc9,
0x3dd5bd8e,0x3de23d71,0xbd84bddc,0xbe003bc9,0xbdedbd44,0xbdc63da2,0x3dfdbc96,0x3d2cbdf1,0x3db5bdb5,0xbd15bdf5,0xbcf93df8,0x3dbe3dac,0x3d443ded,0x3dff3c49,0xbdcebd98,0xbde73d5b,
0x3dfbbcc8,0x3dc63da2,0xbd5bbde7,0xbdf8bcf9,0xbd44bded,0xbdf5bd15,0x3dbe3dac,0x3dfdbc96,0x3db53db5,0x3dffbc49,0xbdf1bd2c,0xbddc3d84,0xbdedbd44,0xbde23d71,0x3e00bbc9,0x3d98bdce,
0x3dfb3cc8,0x3da23dc6,0xbd2cbdf1,0xbddcbd84,0x3d44bded,0xbd15bdf5,0xbbc93e00,0x3d983dce,0xbdb53db5,0xbc493dff,0x3d5bbde7,0xbcf9bdf8,0x3dedbd44,0x3d71bde2,0xbdbe3dac,0xbc963dfd,
0x3dd53d8e,0x3d713de2,0xbcf9bdf8,0xbdacbdbe,0x3dedbd44,0x3da2bdc6,0xbdce3d98,0xbd5b3de7,0xbdb5bdb5,0xbdf5bd15,0x3ddc3d84,0x3e003bc9,0xbd443ded,0x3c493dff,0x3c96bdfd,0xbd2cbdf1,
0x3d8e3dd5,0x3d153df5,0xbc96bdfd,0xbd5bbde7,0x3ded3d44,0x3dff3c49,0xbdf8bcf9,0xbe003bc9,0x3db5bdb5,0x3d71bde2,0xbd983dce,0xbd2c3df1,0xbd44bded,0xbda2bdc6,0x3d843ddc,0x3dbe3dac,
0x3cc83dfb,0x3c493dff,0xbbc9be00,0xbc96bdfd,0x3d443ded,0x3d713de2,0xbd5bbde7,0xbd84bddc,0x3db53db5,0x3dc63da2,0xbdbebdac,0xbdcebd98,0x3ded3d44,0x3df53d15,0xbdf1bd2c,0xbdf8bcf9,
0xbd803d80,0xbdffbc49,0xbe00bbc9,0xbdfdbc96,0xbd8e3dd5,0xbde2bd71,0xbde7bd5b,0xbddcbd84,0xbdd53d8e,0xbda2bdc6,0xbdacbdbe,0xbd98bdce,0xbdfb3cc8,0xbd15bdf5,0xbd2cbdf1,0xbcf9bdf8,
0x3d803d80,0x3df53d15,0x3dfd3c96,0x3de73d5b,0xbdfbbcc8,0x3c493dff,0x3cf93df8,0xbbc93e00,0xbcc8bdfb,0xbde23d71,0xbdce3d98,0xbdf13d2c,0x3dd5bd8e,0xbdc6bda2,0xbddcbd84,0xbdacbdbe,
0xbd803d80,0xbde2bd71,0xbdf8bcf9,0xbdbebdac,0xbcc8bdfb,0x3dc6bda2,0x3d98bdce,0x3de7bd5b,0x3dfb3cc8,0x3d153df5,0x3d843ddc,0x3bc93e00,0xbd8e3dd5,0xbdffbc49,0xbdfd3c96,0xbdf1bd2c,
0x3d803d80,0x3dc63da2,0x3df13d2c,0x3d843ddc,0x3dd5bd8e,0xbdf5bd15,0xbe003bc9,0xbdcebd98,0xbd8e3dd5,0x3dffbc49,0x3de7bd5b,0x3df83cf9,0x3cc8bdfb,0xbde23d71,0xbdac3dbe,0xbdfd3c96,
0xbd803d80,0xbda2bdc6,0xbde7bd5b,0xbcf9bdf8,0x3dd53d8e,0x3d153df5,0x3dac3dbe,0xbc963dfd,0xbd8ebdd5,0x3c49bdff,0xbd2cbdf1,0x3d84bddc,0x3cc83dfb,0xbd713de2,0xbbc93e00,0xbdce3d98,
0x3d803d80,0x3d713de2,0x3ddc3d84,0xbbc93e00,0xbcc83dfb,0x3da2bdc6,0x3c96bdfd,0x3df1bd2c,0x3dfbbcc8,0xbdf5bd15,0xbdf83cf9,0xbdacbdbe,0xbd8ebdd5,0x3c493dff,0x3d983dce,0xbd5b3de7,
0xbd803d80,0xbd15bdf5,0xbdcebd98,0x3d2cbdf1,0xbdfb3cc8,0xbdffbc49,0xbddc3d84,0xbdbebdac,0xbcc83dfb,0xbd713de2,0x3c963dfd,0xbde73d5b,0x3dd53d8e,0x3da23dc6,0x3df83cf9,0x3bc93e00,
0x3d803d80,0x3c493dff,0x3dbe3dac,0xbd983dce,0xbd8ebdd5,0x3d713de2,0x3df13d2c,0xbcf93df8,0xbdd5bd8e,0x3dc63da2,0x3e00bbc9,0x3c963dfd,0xbdfbbcc8,0x3df53d15,0x3de7bd5b,0x3d843ddc,
0xbd803d80,0x3c49bdff,0xbdacbdbe,0x3dcebd98,0x3d8ebdd5,0x3d71bde2,0xbd2cbdf1,0x3df8bcf9,0x3dd5bd8e,0x3dc6bda2,0x3bc9be00,0x3dfd3c96,0x3dfbbcc8,0x3df5bd15,0x3d5bbde7,0x3ddc3d84,
0x3d803d80,0xbd153df5,0x3d983dce,0xbdf13d2c,0x3dfb3cc8,0xbdff3c49,0xbd843ddc,0xbdacbdbe,0x3cc83dfb,0xbd71bde2,0xbdfdbc96,0x3d5bbde7,0xbdd53d8e,0x3da2bdc6,0xbcf9bdf8,0x3e003bc9,
0xbd803d80,0x3d71bde2,0xbd84bddc,0x3e00bbc9,0x3cc83dfb,0x3da23dc6,0x3dfdbc96,0xbd2c3df1,0xbdfbbcc8,0xbdf53d15,0xbcf93df8,0xbdbebdac,0x3d8ebdd5,0x3c49bdff,0xbdcebd98,0x3de7bd5b,
0x3d803d80,0xbda23dc6,0x3d5b3de7,0xbdf8bcf9,0xbdd53d8e,0x3d15bdf5,0xbdbebdac,0x3dfdbc96,0x3d8ebdd5,0x3c493dff,0x3df13d2c,0xbddc3d84,0xbcc83dfb,0xbd71bde2,0xbe003bc9,0x3d98bdce,
0xbd803d80,0x3dc6bda2,0xbd2cbdf1,0x3ddc3d84,0xbdd5bd8e,0xbdf53d15,0xbbc93e00,0xbd98bdce,0x3d8e3dd5,0x3dff3c49,0x3d5bbde7,0x3cf93df8,0xbcc8bdfb,0xbde2bd71,0xbdbe3dac,0x3c96bdfd,
0x3d803d80,0xbde23d71,0x3cf93df8,0xbdacbdbe,0x3cc8bdfb,0x3dc63da2,0x3dcebd98,0xbd5b3de7,0xbdfb3cc8,0x3d15bdf5,0xbddcbd84,0x3e003bc9,0x3d8e3dd5,0xbdff3c49,0xbc963dfd,0xbd2cbdf1,
0xbd803d80,0x3df5bd15,0xbc96bdfd,0x3d5b3de7,0x3dfbbcc8,0x3c49bdff,0xbdf8bcf9,0x3e00bbc9,0x3cc8bdfb,0xbde2bd71,0xbd983dce,0x3d2cbdf1,0xbdd5bd8e,0xbdc63da2,0x3d843ddc,0xbdbebdac,
0x3d803d80,0xbdff3c49,0x3bc93e00,0xbc96bdfd,0x3d8e3dd5,0xbde23d71,0x3d5b3de7,0xbd84bddc,0x3dd53d8e,0xbda23dc6,0x3dbe3dac,0xbdcebd98,0x3dfb3cc8,0xbd153df5,0x3df13d2c,0xbdf8bcf9,
0xbd803d80,0x3dff3c49,0x3bc9be00,0xbc963dfd,0xbd8e3dd5,0x3de23d71,0x3d5bbde7,0xbd843ddc,0xbdd53d8e,0x3da23dc6,0x3dbebdac,0xbdce3d98,0xbdfb3cc8,0x3d153df5,0x3df1bd2c,0xbdf83cf9,
0x3d803d80,0xbdf5bd15,0xbc963dfd,0x3d5bbde7,0xbdfbbcc8,0xbc49bdff,0xbdf83cf9,0x3e003bc9,0xbcc8bdfb,0x3de2bd71,0xbd98bdce,0x3d2c3df1,0x3dd5bd8e,0x3dc63da2,0x3d84bddc,0xbdbe3dac,
0xbd803d80,0x3de23d71,0x3cf9bdf8,0xbdac3dbe,0xbcc8bdfb,0xbdc63da2,0x3dce3d98,0xbd5bbde7,0x3dfb3cc8,0xbd15bdf5,0xbddc3d84,0x3e00bbc9,0xbd8e3dd5,0x3dff3c49,0xbc96bdfd,0xbd2c3df1,
0x3d803d80,0xbdc6bda2,0xbd2c3df1,0x3ddcbd84,0x3dd5bd8e,0x3df53d15,0xbbc9be00,0xbd983dce,0xbd8e3dd5,0xbdff3c49,0x3d5b3de7,0x3cf9bdf8,0x3cc8bdfb,0x3de2bd71,0xbdbebdac,0x3c963dfd,
0xbd803d80,0x3da23dc6,0x3d5bbde7,0xbdf83cf9,0x3dd53d8e,0xbd15bdf5,0xbdbe3dac,0x3dfd3c96,0xbd8ebdd5,0xbc493dff,0x3df1bd2c,0xbddcbd84,0x3cc83dfb,0x3d71bde2,0xbe00bbc9,0x3d983dce,
0x3d803d80,0xbd71bde2,0xbd843ddc,0x3e003bc9,0xbcc83dfb,0xbda23dc6,0x3dfd3c96,0xbd2cbdf1,0x3dfbbcc8,0x3df53d15,0xbcf9bdf8,0xbdbe3dac,0xbd8ebdd5,0xbc49bdff,0xbdce3d98,0x3de73d5b,
0xbd803d80,0x3d153df5,0x3d98bdce,0xbdf1bd2c,0xbdfb3cc8,0x3dff3c49,0xbd84bddc,0xbdac3dbe,0xbcc83dfb,0x3d71bde2,0xbdfd3c96,0x3d5b3de7,0x3dd53d8e,0xbda2bdc6,0xbcf93df8,0x3e00bbc9,
0x3d803d80,0xbc49bdff,0xbdac3dbe,0x3dce3d98,0xbd8ebdd5,0xbd71bde2,0xbd2c3df1,0x3df83cf9,0xbdd5bd8e,0xbdc6bda2,0x3bc93e00,0x3dfdbc96,0xbdfbbcc8,0xbdf5bd15,0x3d5b3de7,0x3ddcbd84,
0xbd803d80,0xbc493dff,0x3dbebdac,0xbd98bdce,0x3d8ebdd5,0xbd713de2,0x3df1bd2c,0xbcf9bdf8,0x3dd5bd8e,0xbdc63da2,0x3e003bc9,0x3c96bdfd,0x3dfbbcc8,0xbdf53d15,0x3de73d5b,0x3d84bddc,
0x3d803d80,0x3d15bdf5,0xbdce3d98,0x3d2c3df1,0x3dfb3cc8,0x3dffbc49,0xbddcbd84,0xbdbe3dac,0x3cc83dfb,0x3d713de2,0x3c96bdfd,0xbde7bd5b,0xbdd53d8e,0xbda23dc6,0x3df8bcf9,0x3bc9be00,
0xbd803d80,0xbd713de2,0x3ddcbd84,0xbbc9be00,0x3cc83dfb,0xbda2bdc6,0x3c963dfd,0x3df13d2c,0xbdfbbcc8,0x3df5bd15,0xbdf8bcf9,0xbdac3dbe,0x3d8ebdd5,0xbc493dff,0x3d98bdce,0xbd5bbde7,
0x3d803d80,0x3da2bdc6,0xbde73d5b,0xbcf93df8,0xbdd53d8e,0xbd153df5,0x3dacbdbe,0xbc96bdfd,0x3d8ebdd5,0xbc49bdff,0xbd2c3df1,0x3d843ddc,0xbcc83dfb,0x3d713de2,0xbbc9be00,0xbdcebd98,
0xbd803d80,0xbdc63da2,0x3df1bd2c,0x3d84bddc,0xbdd5bd8e,0x3df5bd15,0xbe00bbc9,0xbdce3d98,0x3d8e3dd5,0xbdffbc49,0x3de73d5b,0x3df8bcf9,0xbcc8bdfb,0x3de23d71,0xbdacbdbe,0xbdfdbc96,
0x3d803d80,0x3de2bd71,0xbdf83cf9,0xbdbe3dac,0x3cc8bdfb,0xbdc6bda2,0x3d983dce,0x3de73d5b,0xbdfb3cc8,0xbd153df5,0x3d84bddc,0x3bc9be00,0x3d8e3dd5,0x3dffbc49,0xbdfdbc96,0xbdf13d2c,
0xbd803d80,0xbdf53d15,0x3dfdbc96,0x3de7bd5b,0x3dfbbcc8,0xbc493dff,0x3cf9bdf8,0xbbc9be00,0x3cc8bdfb,0x3de23d71,0xbdcebd98,0xbdf1bd2c,0xbdd5bd8e,0x3dc6bda2,0xbddc3d84,0xbdac3dbe,
0x3d803d80,0x3dffbc49,0xbe003bc9,0xbdfd3c96,0x3d8e3dd5,0x3de2bd71,0xbde73d5b,0xbddc3d84,0x3dd53d8e,0x3da2bdc6,0xbdac3dbe,0xbd983dce,0x3dfb3cc8,0x3d15bdf5,0xbd2c3df1,0xbcf93df8,
0xbd153df5,0xbc963dfd,0xbc173dff,0xbce03dfa,0xbd8e3dd5,0xbdac3dbe,0xbd9d3dca,0xbdb93db1,0xbded3d44,0xbdf83cf9,0xbdf33d21,0xbdfc3caf,0xbdfbbcc8,0xbdf1bd2c,0xbdf7bd09,0xbdeabd4f,
0xbda23dc6,0xbd2c3df1,0xbcaf3dfc,0xbd7c3ddf,0xbdfb3cc8,0xbdfdbc96,0xbe003b49,0xbdf3bd21,0xbd44bded,0xbbc9be00,0xbce0bdfa,0x3c7bbdfe,0x3dd5bd8e,0x3df8bcf9,0x3deabd4f,0x3dffbc17,
0xbde23d71,0xbd843ddc,0xbd093df7,0xbdb93db1,0xbdd5bd8e,0xbd5bbde7,0xbda7bdc2,0xbcafbdfc,0x3dedbd44,0x3dfd3c96,0x3dfebc7b,0x3dea3d4f,0xbcc83dfb,0xbdac3dbe,0xbd663de5,0xbdd83d89,
0xbdff3c49,0xbdac3dbe,0xbd383def,0xbde53d66,0xbcc8bdfb,0x3d84bddc,0x3cafbdfc,0x3dcabd9d,0x3d443ded,0xbd2c3df1,0x3b493e00,0xbda73dc2,0xbd8ebdd5,0x3c96bdfd,0xbce0bdfa,0x3d7cbddf,
0xbdf5bd15,0xbdce3d98,0xbd663de5,0xbdfc3caf,0x3d8ebdd5,0x3e00bbc9,0x3ddfbd7c,0x3dea3d4f,0xbded3d44,0xbddcbd84,0xbdffbc17,0xbd89bdd8,0x3dfb3cc8,0x3d5b3de7,0x3dca3d9d,0xbb493e00,
0xbdc6bda2,0xbde73d5b,0xbd893dd8,0xbdfebc7b,0x3dfbbcc8,0x3d983dce,0x3def3d38,0x3c173dff,0xbd44bded,0x3dacbdbe,0x3cafbdfc,0x3df7bd09,0xbdd53d8e,0xbddcbd84,0xbe003b49,0xbd66bde5,
0xbd71bde2,0xbdf83cf9,0xbd9d3dca,0xbdeabd4f,0x3dd53d8e,0xbd2c3df1,0x3d213df3,0xbdd83d89,0x3dedbd44,0x3d983dce,0x3df73d09,0xbb493e00,0x3cc8bdfb,0x3e00bbc9,0x3dc2bda7,0x3dd13d93,
0xbc49bdff,0xbe003bc9,0xbdb13db9,0xbdc2bda7,0x3cc83dfb,0xbdf83cf9,0xbd893dd8,0xbddfbd7c,0x3d443ded,0xbde73d5b,0xbd383def,0xbdf3bd21,0x3d8e3dd5,0xbdce3d98,0xbcaf3dfc,0xbdfebc7b,
0x3d15bdf5,0xbdfdbc96,0xbdc23da7,0xbd89bdd8,0xbd8e3dd5,0xbdbebdac,0xbdfe3c7b,0x3b49be00,0xbded3d44,0xbcf9bdf8,0xbde5bd66,0x3d93bdd1,0xbdfbbcc8,0x3d2cbdf1,0xbd7cbddf,0x3defbd38,
0x3da2bdc6,0xbdf1bd2c,0xbdd13d93,0xbd09bdf7,0xbdfb3cc8,0x3c96bdfd,0xbdb9bdb1,0x3de5bd66,0xbd44bded,0x3e00bbc9,0x3d89bdd8,0x3d9d3dca,0x3dd5bd8e,0x3cf93df8,0x3def3d38,0xbda73dc2,
0x3de2bd71,0xbddcbd84,0xbddf3d7c,0x3b49be00,0xbdd5bd8e,0x3de7bd5b,0x3c17bdff,0x3dd13d93,0x3dedbd44,0xbc963dfd,0x3dca3d9d,0xbdef3d38,0xbcc83dfb,0xbdbebdac,0xbdf33d21,0x3ce0bdfa,
0x3dffbc49,0xbdbebdac,0xbdea3d4f,0x3d21bdf3,0xbcc8bdfb,0x3ddc3d84,0x3dd1bd93,0xbc7b3dfe,0x3d443ded,0xbdf1bd2c,0xbdb13db9,0xbc17bdff,0xbd8ebdd5,0x3dfd3c96,0x3d89bdd8,0x3d093df7,
0x3df53d15,0xbd98bdce,0xbdf33d21,0x3d93bdd1,0x3d8ebdd5,0x3bc93e00,0x3df73d09,0xbdef3d38,0xbded3d44,0x3d84bddc,0xbda7bdc2,0x3dfa3ce0,0x3dfb3cc8,0xbde73d5b,0x3c7b3dfe,0xbdb1bdb9,
0x3dc63da2,0xbd5bbde7,0xbdfa3ce0,0x3dcabd9d,0x3dfbbcc8,0xbdce3d98,0x3d4f3dea,0xbdc2bda7,0xbd44bded,0x3dbe3dac,0x3dd1bd93,0xbd7c3ddf,0xbdd53d8e,0x3d84bddc,0xbdb9bdb1,0x3df33d21,
0x3d713de2,0xbcf9bdf8,0xbdfe3c7b,0x3defbd38,0x3dd53d8e,0xbdf1bd2c,0xbd663de5,0x3ce0bdfa,0x3dedbd44,0xbdce3d98,0x3d7c3ddf,0xbdb1bdb9,0x3cc8bdfb,0x3bc93e00,0x3dff3c17,0xbdfc3caf,
0x3c493dff,0xbbc9be00,0xbe003b49,0x3dffbc17,0x3cc83dfb,0xbcf9bdf8,0xbdfa3ce0,0x3df7bd09,0x3d443ded,0xbd5bbde7,0xbdea3d4f,0x3de5bd66,0x3d8e3dd5,0xbd98bdce,0xbdd13d93,0x3dcabd9d,
0xbd153df5,0x3c96bdfd,0xbdffbc17,0x3dfa3ce0,0xbd8e3dd5,0x3dacbdbe,0xbdcabd9d,0x3db13db9,0xbded3d44,0x3df8bcf9,0xbd21bdf3,0x3caf3dfc,0xbdfbbcc8,0x3df13d2c,0x3d09bdf7,0xbd4f3dea,
0xbda23dc6,0x3d2cbdf1,0xbdfcbcaf,0x3ddf3d7c,0xbdfb3cc8,0x3dfd3c96,0xbb49be00,0xbd213df3,0xbd44bded,0x3bc93e00,0x3dfabce0,0xbdfebc7b,0x3dd5bd8e,0xbdf83cf9,0x3d4f3dea,0xbc17bdff,
0xbde23d71,0x3d84bddc,0xbdf7bd09,0x3db13db9,0xbdd5bd8e,0x3d5b3de7,0x3dc2bda7,0xbdfc3caf,0x3dedbd44,0xbdfdbc96,0x3c7b3dfe,0x3d4fbdea,0xbcc83dfb,0x3dacbdbe,0xbde5bd66,0x3d893dd8,
0xbdff3c49,0x3dacbdbe,0xbdefbd38,0x3d663de5,0xbcc8bdfb,0xbd843ddc,0x3dfc3caf,0xbd9dbdca,0x3d443ded,0x3d2cbdf1,0xbe003b49,0x3dc23da7,0xbd8ebdd5,0xbc963dfd,0x3dfabce0,0xbddfbd7c,
0xbdf5bd15,0x3dcebd98,0xbde5bd66,0x3caf3dfc,0x3d8ebdd5,0xbe003bc9,0x3d7c3ddf,0x3d4fbdea,0xbded3d44,0x3ddc3d84,0x3c17bdff,0xbdd83d89,0x3dfb3cc8,0xbd5bbde7,0xbd9d3dca,0x3e003b49,
0xbdc6bda2,0x3de7bd5b,0xbdd8bd89,0xbc7b3dfe,0x3dfbbcc8,0xbd98bdce,0xbd383def,0x3dffbc17,0xbd44bded,0xbdac3dbe,0x3dfc3caf,0xbd09bdf7,0xbdd53d8e,0x3ddc3d84,0xbb49be00,0xbde53d66,
0xbd71bde2,0x3df8bcf9,0xbdcabd9d,0xbd4f3dea,0x3dd53d8e,0x3d2cbdf1,0xbdf33d21,0x3d893dd8,0x3dedbd44,0xbd98bdce,0xbd093df7,0x3e003b49,0x3cc8bdfb,0xbe003bc9,0x3da73dc2,0x3d93bdd1,
0xbc49bdff,0x3e00bbc9,0xbdb9bdb1,0xbda73dc2,0x3cc83dfb,0x3df8bcf9,0xbdd8bd89,0xbd7c3ddf,0x3d443ded,0x3de7bd5b,0xbdefbd38,0xbd213df3,0x3d8e3dd5,0x3dcebd98,0xbdfcbcaf,0xbc7b3dfe,
0x3d15bdf5,0x3dfd3c96,0xbda7bdc2,0xbdd83d89,0xbd8e3dd5,0x3dbe3dac,0xbc7bbdfe,0xbe00bb49,0xbded3d44,0x3cf93df8,0x3d66bde5,0xbdd1bd93,0xbdfbbcc8,0xbd2c3df1,0x3ddfbd7c,0xbd38bdef,
0x3da2bdc6,0x3df13d2c,0xbd93bdd1,0xbdf73d09,0xbdfb3cc8,0xbc963dfd,0x3db1bdb9,0xbd66bde5,0xbd44bded,0xbe003bc9,0x3dd83d89,0x3dcabd9d,0x3dd5bd8e,0xbcf9bdf8,0xbd383def,0x3dc23da7,
0x3de2bd71,0x3ddc3d84,0xbd7cbddf,0xbe00bb49,0xbdd5bd8e,0xbde73d5b,0x3dff3c17,0x3d93bdd1,0x3dedbd44,0x3c96bdfd,0xbd9d3dca,0x3d383def,0xbcc83dfb,0x3dbe3dac,0xbd21bdf3,0xbdfabce0,
0x3dffbc49,0x3dbe3dac,0xbd4fbdea,0xbdf3bd21,0xbcc8bdfb,0xbddcbd84,0x3d933dd1,0x3dfe3c7b,0x3d443ded,0x3df13d2c,0xbdb9bdb1,0xbdff3c17,0xbd8ebdd5,0xbdfdbc96,0x3dd83d89,0x3df7bd09,
0x3df53d15,0x3d983dce,0xbd21bdf3,0xbdd1bd93,0x3d8ebdd5,0xbbc9be00,0xbd093df7,0x3d383def,0xbded3d44,0xbd843ddc,0x3dc2bda7,0x3ce0bdfa,0x3dfb3cc8,0x3de7bd5b,0xbdfe3c7b,0xbdb93db1,
0x3dc63da2,0x3d5b3de7,0xbce0bdfa,0xbd9dbdca,0x3dfbbcc8,0x3dcebd98,0xbdea3d4f,0xbda73dc2,0xbd44bded,0xbdbebdac,0x3d933dd1,0x3ddf3d7c,0xbdd53d8e,0xbd843ddc,0x3db1bdb9,0x3d21bdf3,
0x3d713de2,0x3cf93df8,0xbc7bbdfe,0xbd38bdef,0x3dd53d8e,0x3df13d2c,0xbde5bd66,0xbdfabce0,0x3dedbd44,0x3dcebd98,0xbddf3d7c,0xbdb93db1,0x3cc8bdfb,0xbbc9be00,0xbc173dff,0x3caf3dfc,
0x3c493dff,0x3bc93e00,0xbb49be00,0xbc17bdff,0x3cc83dfb,0x3cf93df8,0xbce0bdfa,0xbd09bdf7,0x3d443ded,0x3d5b3de7,0xbd4fbdea,0xbd66bde5,0x3d8e3dd5,0x3d983dce,0xbd93bdd1,0xbd9dbdca,
0xbdb53d80,0xbd98bdce,0xbda7bdc2,0xbd89bdd8,0xbdc63da2,0xbbc9be00,0xbc7bbdfe,0x3b49be00,0xbdff3c49,0x3d84bddc,0x3d66bde5,0x3d93bdd1,0xbde2bd71,0x3de7bd5b,0x3ddfbd7c,0x3defbd38,
0x3db53d80,0x3d5b3de7,0x3d933dd1,0x3d093df7,0xbde2bd71,0xbdce3d98,0xbdb13db9,0xbde53d66,0x3d15bdf5,0xbdbebdac,0xbdd8bd89,0xbd9dbdca,0x3dff3c49,0x3d84bddc,0x3d38bdef,0x3da7bdc2,
0xbdb53d80,0xbcf9bdf8,0xbd7cbddf,0x3b49be00,0x3c49bdff,0x3df13d2c,0x3dff3c17,0x3dd13d93,0x3dc63da2,0xbdce3d98,0xbd9d3dca,0xbdef3d38,0xbdf53d15,0xbbc9be00,0xbd21bdf3,0x3ce0bdfa,
0x3db53d80,0x3bc93e00,0x3d4f3dea,0xbd213df3,0x3df5bd15,0xbcf9bdf8,0xbd93bdd1,0x3c7bbdfe,0xbde23d71,0x3d5b3de7,0x3db93db1,0x3c173dff,0x3dc6bda2,0xbd98bdce,0xbdd8bd89,0xbd09bdf7,
0xbdb53d80,0x3c96bdfd,0xbd21bdf3,0x3d93bdd1,0x3da23dc6,0xbdac3dbe,0xbd093df7,0xbdef3d38,0xbc49bdff,0x3df8bcf9,0x3dc2bda7,0x3dfa3ce0,0xbd713de2,0xbdf1bd2c,0xbdfe3c7b,0xbdb1bdb9,
0x3db53d80,0xbd2c3df1,0x3ce03dfa,0xbdca3d9d,0xbd713de2,0x3dfd3c96,0x3deabd4f,0x3dc23da7,0x3df53d15,0xbbc9be00,0xbd93bdd1,0x3d7cbddf,0x3c49bdff,0xbdf83cf9,0xbdb13db9,0xbdf3bd21,
0xbdb53d80,0x3d84bddc,0xbc7bbdfe,0x3defbd38,0xbdffbc49,0xbd5bbde7,0xbde5bd66,0x3ce0bdfa,0xbda23dc6,0xbdfdbc96,0xbddf3d7c,0xbdb1bdb9,0x3d153df5,0xbdac3dbe,0xbc173dff,0xbdfc3caf,
0x3db53d80,0xbdac3dbe,0x3b493e00,0xbdff3c17,0xbd15bdf5,0xbd843ddc,0x3ce03dfa,0xbdf73d09,0xbd71bde2,0xbd2c3df1,0x3d4f3dea,0xbde53d66,0xbda2bdc6,0xbc963dfd,0x3d933dd1,0xbdca3d9d,
0xbdb53d80,0x3dcebd98,0x3c17bdff,0x3dfa3ce0,0x3dc6bda2,0x3e00bbc9,0x3d9dbdca,0x3db13db9,0x3dffbc49,0x3ddc3d84,0x3df3bd21,0x3caf3dfc,0x3de23d71,0x3d5b3de7,0x3df73d09,0xbd4f3dea,
0x3db53d80,0xbde73d5b,0xbcaf3dfc,0xbddfbd7c,0x3de23d71,0xbd98bdce,0xbe003b49,0x3d21bdf3,0xbd153df5,0x3dacbdbe,0xbce0bdfa,0x3dfe3c7b,0xbdffbc49,0x3ddc3d84,0x3deabd4f,0x3c173dff,
0xbdb53d80,0x3df8bcf9,0x3d09bdf7,0x3db13db9,0xbc493dff,0xbd2c3df1,0x3da73dc2,0xbdfc3caf,0xbdc6bda2,0xbd98bdce,0xbdfe3c7b,0x3d4fbdea,0x3df5bd15,0x3e00bbc9,0x3d66bde5,0x3d893dd8,
0x3db53d80,0xbe003bc9,0xbd383def,0xbd66bde5,0xbdf53d15,0x3df8bcf9,0x3cafbdfc,0x3d9d3dca,0x3de2bd71,0xbde73d5b,0x3b493e00,0xbdc2bda7,0xbdc63da2,0x3dcebd98,0xbce0bdfa,0x3ddf3d7c,
0xbdb53d80,0x3dfd3c96,0x3d66bde5,0x3caf3dfc,0xbda2bdc6,0xbdbebdac,0xbddf3d7c,0x3d4fbdea,0x3c493dff,0x3cf93df8,0x3dff3c17,0xbdd83d89,0x3d71bde2,0x3d2cbdf1,0xbdcabd9d,0x3e003b49,
0x3db53d80,0xbdf1bd2c,0xbd893dd8,0x3c7bbdfe,0x3d71bde2,0xbc963dfd,0x3def3d38,0xbdff3c17,0xbdf5bd15,0x3e00bbc9,0x3cafbdfc,0x3d093df7,0xbc493dff,0xbcf9bdf8,0xbe003b49,0x3de5bd66,
0xbdb53d80,0x3ddc3d84,0x3d9dbdca,0xbd4f3dea,0x3dff3c49,0x3de7bd5b,0xbd21bdf3,0x3d893dd8,0x3da2bdc6,0x3c96bdfd,0xbdf7bd09,0x3e003b49,0xbd15bdf5,0xbdbebdac,0xbdc23da7,0x3d93bdd1,
0x3db53d80,0xbdbebdac,0xbdb13db9,0x3da7bdc2,0x3d153df5,0xbddcbd84,0xbd893dd8,0x3d7cbddf,0x3d713de2,0xbdf1bd2c,0xbd383def,0x3d21bdf3,0x3da23dc6,0xbdfdbc96,0xbcaf3dfc,0x3c7bbdfe,
0xbdb53d80,0x3d983dce,0x3dc2bda7,0xbdd83d89,0xbdc63da2,0x3bc93e00,0x3dfebc7b,0xbe00bb49,0xbdff3c49,0xbd843ddc,0x3de53d66,0xbdd1bd93,0xbde2bd71,0xbde73d5b,0x3d7c3ddf,0xbd38bdef,
0x3db53d80,0xbd5bbde7,0xbdd13d93,0x3df7bd09,0xbde2bd71,0x3dcebd98,0xbdb9bdb1,0x3d663de5,0x3d15bdf5,0x3dbe3dac,0x3d89bdd8,0xbdca3d9d,0x3dff3c49,0xbd843ddc,0x3def3d38,0xbdc2bda7,
0xbdb53d80,0x3cf93df8,0x3ddfbd7c,0xbe00bb49,0x3c49bdff,0xbdf1bd2c,0xbc173dff,0x3d93bdd1,0x3dc63da2,0x3dcebd98,0xbdcabd9d,0x3d383def,0xbdf53d15,0x3bc93e00,0x3df3bd21,0xbdfabce0,
0x3db53d80,0xbbc9be00,0xbdea3d4f,0x3df33d21,0x3df5bd15,0x3cf93df8,0x3dd1bd93,0xbdfebc7b,0xbde23d71,0xbd5bbde7,0xbdb13db9,0x3dffbc17,0x3dc6bda2,0x3d983dce,0x3d89bdd8,0xbdf73d09,
0xbdb53d80,0xbc963dfd,0x3df3bd21,0xbdd1bd93,0x3da23dc6,0x3dacbdbe,0xbdf7bd09,0x3d383def,0xbc49bdff,0xbdf83cf9,0x3da73dc2,0x3ce0bdfa,0xbd713de2,0x3df13d2c,0xbc7bbdfe,0xbdb93db1,
0x3db53d80,0x3d2cbdf1,0xbdfa3ce0,0x3d9d3dca,0xbd713de2,0xbdfdbc96,0x3d4f3dea,0x3da7bdc2,0x3df53d15,0x3bc93e00,0x3dd1bd93,0xbddfbd7c,0x3c49bdff,0x3df8bcf9,0xbdb9bdb1,0xbd213df3,
0xbdb53d80,0xbd843ddc,0x3dfebc7b,0xbd38bdef,0xbdffbc49,0x3d5b3de7,0x3d66bde5,0xbdfabce0,0xbda23dc6,0x3dfd3c96,0xbd7cbddf,0xbdb93db1,0x3d153df5,0x3dacbdbe,0xbdffbc17,0x3caf3dfc,
0x3db53d80,0x3dacbdbe,0xbe003b49,0x3c173dff,0xbd15bdf5,0x3d84bddc,0xbdfa3ce0,0x3d093df7,0xbd71bde2,0x3d2cbdf1,0xbdea3d4f,0x3d663de5,0xbda2bdc6,0x3c96bdfd,0xbdd13d93,0x3d9d3dca,
0xbdb53d80,0xbdce3d98,0x3dff3c17,0x3ce0bdfa,0x3dc6bda2,0xbe003bc9,0x3dca3d9d,0x3db9bdb1,0x3dffbc49,0xbddcbd84,0x3d213df3,0x3dfcbcaf,0x3de23d71,0xbd5bbde7,0xbd093df7,0x3dea3d4f,
0x3db53d80,0x3de7bd5b,0xbdfcbcaf,0xbd7c3ddf,0x3de23d71,0x3d983dce,0xbb49be00,0xbdf3bd21,0xbd153df5,0xbdac3dbe,0x3dfabce0,0x3c7bbdfe,0xbdffbc49,0xbddcbd84,0x3d4f3dea,0x3dffbc17,
0xbdb53d80,0xbdf83cf9,0x3df73d09,0x3db9bdb1,0xbc493dff,0x3d2cbdf1,0xbdc23da7,0x3caf3dfc,0xbdc6bda2,0x3d983dce,0xbc7bbdfe,0xbdeabd4f,0x3df5bd15,0xbe003bc9,0x3de53d66,0x3dd8bd89,
0x3db53d80,0x3e00bbc9,0xbdefbd38,0xbde53d66,0xbdf53d15,0xbdf83cf9,0x3dfc3caf,0x3dcabd9d,0x3de2bd71,0x3de7bd5b,0xbe003b49,0xbda73dc2,0xbdc63da2,0xbdce3d98,0x3dfabce0,0x3d7cbddf,
0xbdb53d80,0xbdfdbc96,0x3de53d66,0x3dfcbcaf,0xbda2bdc6,0x3dbe3dac,0xbd7cbddf,0xbdeabd4f,0x3c493dff,0xbcf9bdf8,0xbc173dff,0x3d893dd8,0x3d71bde2,0xbd2c3df1,0x3d9dbdca,0x3b49be00,
0x3db53d80,0x3df13d2c,0xbdd8bd89,0xbdfebc7b,0x3d71bde2,0x3c96bdfd,0xbd383def,0x3c173dff,0xbdf5bd15,0xbe003bc9,0x3dfc3caf,0x3df7bd09,0xbc493dff,0x3cf93df8,0xbb49be00,0xbd66bde5,
0xbdb53d80,0xbddcbd84,0x3dca3d9d,0x3dea3d4f,0x3dff3c49,0xbde73d5b,0x3df3bd21,0x3dd8bd89,0x3da2bdc6,0xbc963dfd,0x3d09bdf7,0x3b49be00,0xbd15bdf5,0x3dbe3dac,0xbda7bdc2,0xbdd1bd93,
0x3db53d80,0x3dbe3dac,0xbdb9bdb1,0xbdc2bda7,0x3d153df5,0x3ddc3d84,0xbdd8bd89,0xbddfbd7c,0x3d713de2,0x3df13d2c,0xbdefbd38,0xbdf3bd21,0x3da23dc6,0x3dfd3c96,0xbdfcbcaf,0xbdfebc7b,
0x3f800000,0x0,0x3f800000,0x0,0x3f800000,0x0,0x3f800000,0x0,0x3f800000,0x0,0x3f800000,0x0,0x3f800000,0x0,0x3f800000,0x0,
0x3f800000,0x0,0x3f7ffb11,0xbc490e90,0x3f7fec43,0xbcc90ab0,0x3f7fd397,0xbd16c32c,0x3f7fb10f,0xbd48fb30,0x3f7f84ab,0xbd7b2b74,0x3f7f4e6d,0xbd96a905,0x3f7f0e58,0xbdafb680,
0x3f800000,0x0,0x3f7fec43,0xbcc90ab0,0x3f7fb10f,0xbd48fb30,0x3f7f4e6d,0xbd96a905,0x3f7ec46d,0xbdc8bd36,0x3f7e1324,0xbdfab273,0x3f7d3aac,0xbe164083,0x3f7c3b28,0xbe2f10a2,
0x3f800000,0x0,0x3f7fd397,0xbd16c32c,0x3f7f4e6d,0xbd96a905,0x3f7e70b0,0xbde1bc2e,0x3f7d3aac,0xbe164083,0x3f7baccd,0xbe3b6ecf,0x3f79c79d,0xbe605c13,0x3f778bc5,0xbe827dc0,
0x3f800000,0x0,0x3f7fb10f,0xbd48fb30,0x3f7ec46d,0xbdc8bd36,0x3f7d3aac,0xbe164083,0x3f7b14be,0xbe47c5c2,0x3f7853f8,0xbe78cfcc,0x3f74fa0b,0xbe94a031,0x3f710908,0xbeac7cd4,
0x3f800000,0x0,0x3f7f84ab,0xbd7b2b74,0x3f7e1324,0xbdfab273,0x3f7baccd,0xbe3b6ecf,0x3f7853f8,0xbe78cfcc,0x3f740bdd,0xbe9aa086,0x3f6ed89e,0xbeb8442a,0x3f68bf3c,0xbed53641,
0x3f800000,0x0,0x3f7f4e6d,0xbd96a905,0x3f7d3aac,0xbe164083,0x3f79c79d,0xbe605c13,0x3f74fa0b,0xbe94a031,0x3f6ed89e,0xbeb8442a,0x3f676bd8,0xbedae880,0x3f5ebe05,0xbefc5d27,
0x3f800000,0x0,0x3f7f0e58,0xbdafb680,0x3f7c3b28,0xbe2f10a2,0x3f778bc5,0xbe827dc0,0x3f710908,0xbeac7cd4,0x3f68bf3c,0xbed53641,0x3f5ebe05,0xbefc5d27,0x3f531849,0xbf10d3cd,
0x3f800000,0x0,0x3f7b14be,0xbe47c5c2,0x3f6c835e,0xbec3ef15,0x3f54db31,0xbf0e39da,0x3f3504f3,0xbf3504f3,0x3f0e39da,0xbf54db31,0x3ec3ef15,0xbf6c835e,0x3e47c5c2,0xbf7b14be,
0x3f800000,0x0,0x3f7a7302,0xbe541501,0x3f6a09a7,0xbecf7bca,0x3f4f7a1f,0xbf15f6d9,0x3f2beb4a,0xbf3daef9,0x3f00e7e4,0xbf5d2d53,0x3ea09ae5,0xbf731447,0x3de1bc2e,0xbf7e70b0,
0x3f800000,0x0,0x3f79c79d,0xbe605c13,0x3f676bd8,0xbedae880,0x3f49d112,0xbf1d7fd1,0x3f226799,0xbf45e403,0x3ee63375,0xbf64aa59,0x3e78cfcc,0xbf7853f8,0x3cc90ab0,0xbf7fec43,
0x3f800000,0x0,0x3f791298,0xbe6c9a7f,0x3f64aa59,0xbee63375,0x3f43e200,0xbf24d225,0x3f187fc0,0xbf4d9f02,0x3ec9b953,0xbf6b4b0c,0x3e2f10a2,0xbf7c3b28,0xbd7b2b74,0xbf7f84ab,
0x3f800000,0x0,0x3f7853f8,0xbe78cfcc,0x3f61c598,0xbef15aea,0x3f3daef9,0xbf2beb4a,0x3f0e39da,0xbf54db31,0x3eac7cd4,0xbf710908,0x3dc8bd36,0xbf7ec46d,0xbe164083,0xbf7d3aac,
0x3f800000,0x0,0x3f778bc5,0xbe827dc0,0x3f5ebe05,0xbefc5d27,0x3f373a23,0xbf32c8c9,0x3f039c3d,0xbf5b941a,0x3e8e9a22,0xbf75dec6,0x3cc90ab0,0xbf7fec43,0xbe6c9a7f,0xbf791298,
0x3f800000,0x0,0x3f76ba07,0xbe888e93,0x3f5b941a,0xbf039c3d,0x3f3085bb,0xbf396842,0x3ef15aea,0xbf61c598,0x3e605c13,0xbf79c79d,0xbd48fb30,0xbf7fb10f,0xbea09ae5,0xbf731447,
0x3f800000,0x0,0x3f75dec6,0xbe8e9a22,0x3f584853,0xbf08f59b,0x3f299415,0xbf3fc767,0x3edae880,0xbf676bd8,0x3e22abb6,0xbf7cbfc9,0xbdfab273,0xbf7e1324,0xbec9b953,0xbf6b4b0c,
0x3f800000,0x0,0x3f7ec46d,0xbdc8bd36,0x3f7b14be,0xbe47c5c2,0x3f74fa0b,0xbe94a031,0x3f6c835e,0xbec3ef15,0x3f61c598,0xbef15aea,0x3f54db31,0xbf0e39da,0x3f45e403,0xbf226799,
0x3f800000,0x0,0x3f6b4b0c,0xbec9b953,0x3f3085bb,0xbf396842,0x3eb263ef,0xbf6ff573,0xbd48fb30,0xbf7fb10f,0xbee0924f,0xbf660f88,0xbf41d870,0xbf273656,0xbf740bdd,0xbe9aa086,
0x3f800000,0x0,0x3f6a09a7,0xbecf7bca,0x3f2beb4a,0xbf3daef9,0x3ea09ae5,0xbf731447,0xbdc8bd36,0xbf7ec46d,0xbefc5d27,0xbf5ebe05,0xbf4d9f02,0xbf187fc0,0xbf79c79d,0xbe605c13,
0x3f800000,0x0,0x3f68bf3c,0xbed53641,0x3f273656,0xbf41d870,0x3e8e9a22,0xbf75dec6,0xbe164083,0xbf7d3aac,0xbf0b9a6b,0xbf5695e5,0xbf584853,0xbf08f59b,0xbf7dabcc,0xbe09cf86,
0x3f800000,0x0,0x3f676bd8,0xbedae880,0x3f226799,0xbf45e403,0x3e78cfcc,0xbf7853f8,0xbe47c5c2,0xbf7b14be,0xbf187fc0,0xbf4d9f02,0xbf61c598,0xbef15aea,0xbf7fb10f,0xbd48fb30,
0x3f800000,0x0,0x3f660f88,0xbee0924f,0x3f1d7fd1,0xbf49d112,0x3e541501,0xbf7a7302,0xbe78cfcc,0xbf7853f8,0xbf24d225,0xbf43e200,0xbf6a09a7,0xbecf7bca,0xbf7fd397,0x3d16c32c,
0x3f800000,0x0,0x3f64aa59,0xbee63375,0x3f187fc0,0xbf4d9f02,0x3e2f10a2,0xbf7c3b28,0xbe94a031,0xbf74fa0b,0xbf3085bb,0xbf396842,0xbf710908,0xbeac7cd4,0xbf7e1324,0x3dfab273,
0x3f800000,0x0,0x3f633c5a,0xbeebcbbb,0x3f13682a,0xbf514d3d,0x3e09cf86,0xbf7dabcc,0xbeac7cd4,0xbf710908,0xbf3b8f3b,0xbf2e3bde,0xbf76ba07,0xbe888e93,0xbf7a7302,0x3e541501,
0x3f800000,0x0,0x3f74fa0b,0xbe94a031,0x3f54db31,0xbf0e39da,0x3f226799,0xbf45e403,0x3ec3ef15,0xbf6c835e,0x3dc8bd36,0xbf7ec46d,0xbe47c5c2,0xbf7b14be,0xbef15aea,0xbf61c598,
0x3f800000,0x0,0x3f531849,0xbf10d3cd,0x3eb8442a,0xbf6ed89e,0xbe6c9a7f,0xbf791298,0xbf3daef9,0xbf2beb4a,0xbf7dabcc,0xbe09cf86,0xbf64aa59,0x3ee63375,0xbef6e0cb,0x3f604621,
0x3f800000,0x0,0x3f514d3d,0xbf13682a,0x3eac7cd4,0xbf710908,0xbe888e93,0xbf76ba07,0xbf45e403,0xbf226799,0xbf7f4e6d,0xbd96a905,0xbf5b941a,0x3f039c3d,0xbecf7bca,0x3f6a09a7,
0x3f800000,0x0,0x3f4f7a1f,0xbf15f6d9,0x3ea09ae5,0xbf731447,0xbe9aa086,0xbf740bdd,0xbf4d9f02,0xbf187fc0,0xbf7ffb11,0xbc490e90,0xbf514d3d,0x3f13682a,0xbea68f12,0x3f721352,
0x3f800000,0x0,0x3f4d9f02,0xbf187fc0,0x3e94a031,0xbf74fa0b,0xbeac7cd4,0xbf710908,0xbf54db31,0xbf0e39da,0xbf7fb10f,0x3d48fb30,0xbf45e403,0x3f226799,0xbe78cfcc,0x3f7853f8,
0x3f800000,0x0,0x3f4bbbf8,0xbf1b02c6,0x3e888e93,0xbf76ba07,0xbebe1d4a,0xbf6db293,0xbf5b941a,0xbf039c3d,0xbf7e70b0,0x3de1bc2e,0xbf396842,0x3f3085bb,0xbe22abb6,0x3f7cbfc9,
0x3f800000,0x0,0x3f49d112,0xbf1d7fd1,0x3e78cfcc,0xbf7853f8,0xbecf7bca,0xbf6a09a7,0xbf61c598,0xbef15aea,0xbf7c3b28,0x3e2f10a2,0xbf2beb4a,0x3f3daef9,0xbd96a905,0x3f7f4e6d,
0x3f800000,0x0,0x3f47de65,0xbf1ff6cb,0x3e605c13,0xbf79c79d,0xbee0924f,0xbf660f88,0xbf676bd8,0xbedae880,0xbf791298,0x3e6c9a7f,0xbf1d7fd1,0x3f49d112,0x3c490e90,0x3f7ffb11,
0x3f800000,0x0,0x3f800000,0x0,0x3f800000,0x0,0x3f800000,0x0,0x40000000,0x0,0x3f800000,0x0,0x3f800000,0x0,0x3f800000,0x0,
0x3f800000,0x0,0x3f7ffb11,0xbc490e90,0x3f7fec43,0xbcc90ab0,0x3f7fd397,0xbd16c32c,0x3fffb10f,0xbdc8fb30,0x3f7f84ab,0xbd7b2b74,0x3f7f4e6d,0xbd96a905,0x3f7f0e58,0xbdafb680,
0x3f800000,0x0,0x3f7fec43,0xbcc90ab0,0x3f7fb10f,0xbd48fb30,0x3f7f4e6d,0xbd96a905,0x3ffec46d,0xbe48bd36,0x3f7e1324,0xbdfab273,0x3f7d3aac,0xbe164083,0x3f7c3b28,0xbe2f10a2,
0x3f800000,0x0,0x3f7fd397,0xbd16c32c,0x3f7f4e6d,0xbd96a905,0x3f7e70b0,0xbde1bc2e,0x3ffd3aac,0xbe964083,0x3f7baccd,0xbe3b6ecf,0x3f79c79d,0xbe605c13,0x3f778bc5,0xbe827dc0,
0x3f800000,0x0,0x3f7fb10f,0xbd48fb30,0x3f7ec46d,0xbdc8bd36,0x3f7d3aac,0xbe164083,0x3ffb14be,0xbec7c5c2,0x3f7853f8,0xbe78cfcc,0x3f74fa0b,0xbe94a031,0x3f710908,0xbeac7cd4,
0x3f800000,0x0,0x3f7f84ab,0xbd7b2b74,0x3f7e1324,0xbdfab273,0x3f7baccd,0xbe3b6ecf,0x3ff853f8,0xbef8cfcc,0x3f740bdd,0xbe9aa086,0x3f6ed89e,0xbeb8442a,0x3f68bf3c,0xbed53641,
0x3f800000,0x0,0x3f7f4e6d,0xbd96a905,0x3f7d3aac,0xbe164083,0x3f79c79d,0xbe605c13,0x3ff4fa0b,0xbf14a031,0x3f6ed89e,0xbeb8442a,0x3f676bd8,0xbedae880,0x3f5ebe05,0xbefc5d27,
0x3f800000,0x0,0x3f7f0e58,0xbdafb680,0x3f7c3b28,0xbe2f10a2,0x3f778bc5,0xbe827dc0,0x3ff10908,0xbf2c7cd4,0x3f68bf3c,0xbed53641,0x3f5ebe05,0xbefc5d27,0x3f531849,0xbf10d3cd,
0x3f800000,0x0,0x3f7ec46d,0xbdc8bd36,0x3f7b14be,0xbe47c5c2,0x3f74fa0b,0xbe94a031,0x3fec835e,0xbf43ef15,0x3f61c598,0xbef15aea,0x3f54db31,0xbf0e39da,0x3f45e403,0xbf226799,
0x3f800000,0x0,0x3f7e70b0,0xbde1bc2e,0x3f79c79d,0xbe605c13,0x3f721352,0xbea68f12,0x3fe76bd8,0xbf5ae880,0x3f59f26a,0xbf064b82,0x3f49d112,0xbf1d7fd1,0x3f373a23,0xbf32c8c9,
0x3f800000,0x0,0x3f7e1324,0xbdfab273,0x3f7853f8,0xbe78cfcc,0x3f6ed89e,0xbeb8442a,0x3fe1c598,0xbf715aea,0x3f514d3d,0xbf13682a,0x3f3daef9,0xbf2beb4a,0x3f273656,0xbf41d870,
0x3f800000,0x0,0x3f7dabcc,0xbe09cf86,0x3f76ba07,0xbe888e93,0x3f6b4b0c,0xbec9b953,0x3fdb941a,0xbf839c3d,0x3f47de65,0xbf1ff6cb,0x3f3085bb,0xbf396842,0x3f15f6d9,0xbf4f7a1f,
0x3f800000,0x0,0x3f7d3aac,0xbe164083,0x3f74fa0b,0xbe94a031,0x3f676bd8,0xbedae880,0x3fd4db31,0xbf8e39da,0x3f3daef9,0xbf2beb4a,0x3f226799,0xbf45e403,0x3f039c3d,0xbf5b941a,
0x3f800000,0x0,0x3f7cbfc9,0xbe22abb6,0x3f731447,0xbea09ae5,0x3f633c5a,0xbeebcbbb,0x3fcd9f02,0xbf987fc0,0x3f32c8c9,0xbf373a23,0x3f13682a,0xbf514d3d,0x3ee0924f,0xbf660f88,
0x3f800000,0x0,0x3f7c3b28,0xbe2f10a2,0x3f710908,0xbeac7cd4,0x3f5ebe05,0xbefc5d27,0x3fc5e403,0xbfa26799,0x3f273656,0xbf41d870,0x3f039c3d,0xbf5b941a,0x3eb8442a,0xbf6ed89e,
0x3f800000,0x0,0x3f7baccd,0xbe3b6ecf,0x3f6ed89e,0xbeb8442a,0x3f59f26a,0xbf064b82,0x3fbdaef9,0xbfabeb4a,0x3f1b02c6,0xbf4bbbf8,0x3ee63375,0xbf64aa59,0x3e8e9a22,0xbf75dec6,
0x3f800000,0x0,0x3f7b14be,0xbe47c5c2,0x3f6c835e,0xbec3ef15,0x3f54db31,0xbf0e39da,0x3fb504f3,0xbfb504f3,0x3f0e39da,0xbf54db31,0x3ec3ef15,0xbf6c835e,0x3e47c5c2,0xbf7b14be,
0x3f800000,0x0,0x3f7a7302,0xbe541501,0x3f6a09a7,0xbecf7bca,0x3f4f7a1f,0xbf15f6d9,0x3fabeb4a,0xbfbdaef9,0x3f00e7e4,0xbf5d2d53,0x3ea09ae5,0xbf731447,0x3de1bc2e,0xbf7e70b0,
0x3f800000,0x0,0x3f79c79d,0xbe605c13,0x3f676bd8,0xbedae880,0x3f49d112,0xbf1d7fd1,0x3fa26799,0xbfc5e403,0x3ee63375,0xbf64aa59,0x3e78cfcc,0xbf7853f8,0x3cc90ab0,0xbf7fec43,
0x3f800000,0x0,0x3f791298,0xbe6c9a7f,0x3f64aa59,0xbee63375,0x3f43e200,0xbf24d225,0x3f987fc0,0xbfcd9f02,0x3ec9b953,0xbf6b4b0c,0x3e2f10a2,0xbf7c3b28,0xbd7b2b74,0xbf7f84ab,
0x3f800000,0x0,0x3f7853f8,0xbe78cfcc,0x3f61c598,0xbef15aea,0x3f3daef9,0xbf2beb4a,0x3f8e39da,0xbfd4db31,0x3eac7cd4,0xbf710908,0x3dc8bd36,0xbf7ec46d,0xbe164083,0xbf7d3aac,
0x3f800000,0x0,0x3f778bc5,0xbe827dc0,0x3f5ebe05,0xbefc5d27,0x3f373a23,0xbf32c8c9,0x3f839c3d,0xbfdb941a,0x3e8e9a22,0xbf75dec6,0x3cc90ab0,0xbf7fec43,0xbe6c9a7f,0xbf791298,
0x3f800000,0x0,0x3f76ba07,0xbe888e93,0x3f5b941a,0xbf039c3d,0x3f3085bb,0xbf396842,0x3f715aea,0xbfe1c598,0x3e605c13,0xbf79c79d,0xbd48fb30,0xbf7fb10f,0xbea09ae5,0xbf731447,
0x3f800000,0x0,0x3f75dec6,0xbe8e9a22,0x3f584853,0xbf08f59b,0x3f299415,0xbf3fc767,0x3f5ae880,0xbfe76bd8,0x3e22abb6,0xbf7cbfc9,0xbdfab273,0xbf7e1324,0xbec9b953,0xbf6b4b0c,
0x3f800000,0x0,0x3f74fa0b,0xbe94a031,0x3f54db31,0xbf0e39da,0x3f226799,0xbf45e403,0x3f43ef15,0xbfec835e,0x3dc8bd36,0xbf7ec46d,0xbe47c5c2,0xbf7b14be,0xbef15aea,0xbf61c598,
0x3f800000,0x0,0x3f740bdd,0xbe9aa086,0x3f514d3d,0xbf13682a,0x3f1b02c6,0xbf4bbbf8,0x3f2c7cd4,0xbff10908,0x3d16c32c,0xbf7fd397,0xbe888e93,0xbf76ba07,0xbf0b9a6b,0xbf5695e5,
0x3f800000,0x0,0x3f731447,0xbea09ae5,0x3f4d9f02,0xbf187fc0,0x3f13682a,0xbf514d3d,0x3f14a031,0xbff4fa0b,0xbcc90ab0,0xbf7fec43,0xbeac7cd4,0xbf710908,0xbf1d7fd1,0xbf49d112,
0x3f800000,0x0,0x3f721352,0xbea68f12,0x3f49d112,0xbf1d7fd1,0x3f0b9a6b,0xbf5695e5,0x3ef8cfcc,0xbff853f8,0xbdafb680,0xbf7f0e58,0xbecf7bca,0xbf6a09a7,0xbf2e3bde,0xbf3b8f3b,
0x3f800000,0x0,0x3f710908,0xbeac7cd4,0x3f45e403,0xbf226799,0x3f039c3d,0xbf5b941a,0x3ec7c5c2,0xbffb14be,0xbe164083,0xbf7d3aac,0xbef15aea,0xbf61c598,0xbf3daef9,0xbf2beb4a,
0x3f800000,0x0,0x3f6ff573,0xbeb263ef,0x3f41d870,0xbf273656,0x3ef6e0cb,0xbf604621,0x3e964083,0xbffd3aac,0xbe541501,0xbf7a7302,0xbf08f59b,0xbf584853,0xbf4bbbf8,0xbf1b02c6,
0x3f800000,0x0,0x3f6ed89e,0xbeb8442a,0x3f3daef9,0xbf2beb4a,0x3ee63375,0xbf64aa59,0x3e48bd36,0xbffec46d,0xbe888e93,0xbf76ba07,0xbf187fc0,0xbf4d9f02,0xbf584853,0xbf08f59b,
0x3f800000,0x0,0x3f6db293,0xbebe1d4a,0x3f396842,0xbf3085bb,0x3ed53641,0xbf68bf3c,0x3dc8fb30,0xbfffb10f,0xbea68f12,0xbf721352,0xbf273656,0xbf41d870,0xbf633c5a,0xbeebcbbb,
0x3f800000,0x0,0x3f7fffb1,0xbb490fc6,0x3f7ffec4,0xbbc90f88,0x3f7ffd39,0xbc16cb58,0x3ffffb11,0xbcc90e90,0x3f7ff84a,0xbc7b514b,0x3f7ff4e6,0xbc96c9b6,0x3f7ff0e3,0xbcafea69,
0x3f800000,0x0,0x3f7ff84a,0xbc7b514b,0x3f7fe129,0xbcfb49ba,0x3f7fba9e,0xbd3c6dd5,0x3fff84ab,0xbdfb2b74,0x3f7f3f54,0xbd9cecf9,0x3f7eea9d,0xbdbc3ac3,0x3f7e868b,0xbddb7d37,
0x3f800000,0x0,0x3f7fe705,0xbce22a7a,0x3f7f9c18,0xbd621469,0x3f7f1f49,0xbda973ba,0x3ffe70b0,0xbe61bc2e,0x3f7d906e,0xbe0cec4a,0x3f7c7eb0,0xbe28defc,0x3f7b3bab,0xbe44b0b9,
0x3f800000,0x0,0x3f7fcbe2,0xbd2351cb,0x3f7f2f9d,0xbda3308c,0x3f7e2b72,0xbdf475c0,0x3ffcbfc9,0xbea2abb6,0x3f7aed37,0xbe4ada4f,0x3f78b47b,0xbe72b651,0x3f76167a,0xbe8d17c0,
0x3f800000,0x0,0x3f7fa6e3,0xbd55880e,0x3f7e9bc9,0xbdd53db9,0x3f7cdf6c,0xbe1f917b,0x3ffa7302,0xbed41501,0x3f77583a,0xbe840270,0x3f73913f,0xbe9d9e78,0x3f6f20b0,0xbeb6ccc3,
0x3f800000,0x0,0x3f7f7808,0xbd83db0a,0x3f7de0b1,0xbe039502,0x3f7b3bab,0xbe44b0b9,0x3ff78bc5,0xbf027dc0,0x3f72d4eb,0xbea21887,0x3f6d1c1d,0xbec1071e,0x3f666771,0xbedf28a9,
0x3f800000,0x0,0x3f7f3f54,0xbd9cecf9,0x3f7cfe73,0xbe1c76de,0x3f7940c0,0xbe698bba,0x3ff40bdd,0xbf1aa086,0x3f6d67a1,0xbebf926f,0x3f655e0b,0xbee363fa,0x3f5bfb34,0xbf02ef9f,
0x3f800000,0x0,0x3f7efcc9,0xbdb5f8da,0x3f7bf531,0xbe354098,0x3f76ef5b,0xbe870ada,0x3feff573,0xbf3263ef,0x3f671599,0xbedc53c1,0x3f5c61c7,0xbf0242b1,0x3f4fefa8,0xbf1553b7,
0x3f800000,0x0,0x3f7eb069,0xbdcefdb7,0x3f7ac516,0xbe4dee60,0x3f74484b,0xbe9920fe,0x3feb4b0c,0xbf49b953,0x3f5fe4e9,0xbef840c8,0x3f5233c6,0xbf121eb0,0x3f425b89,0xbf269de3,
0x3f800000,0x0,0x3f7e5a38,0xbde7fa9a,0x3f796e4e,0xbe667c66,0x3f714c7a,0xbeab0201,0x3fe60f88,0xbf60924f,0x3f57dc7f,0xbf099f4e,0x3f46e22a,0xbf212ff9,0x3f33587a,0xbf36ad7f,
0x3f800000,0x0,0x3f7dfa38,0xbe007745,0x3f77f110,0xbe7ee6e1,0x3f6dfcf2,0xbebca7af,0x3fe04621,0xbf76e0cb,0x3f4f0417,0xbf16999f,0x3f3a7ca4,0xbf2f61a5,0x3f2302d3,0xbf456439,
0x3f800000,0x0,0x3f7d906e,0xbe0cec4a,0x3f764d97,0xbe8b9507,0x3f6a5ad9,0xbece0bea,0x3fd9f26a,0xbf864b82,0x3f456439,0xbf2302d3,0x3f2d1469,0xbf3ca003,0x3f11796b,0xbf52a649,
0x3f800000,0x0,0x3f7d1cdd,0xbe195be0,0x3f748422,0xbe97a117,0x3f666771,0xbedf28a9,0x3fd31849,0xbf90d3cd,0x3f3b0629,0xbf2ecef7,0x3f1ebc12,0xbf48d8b3,0x3efdbabb,0xbf5e5aa6,
0x3f800000,0x0,0x3f7c9f8a,0xbe25c58c,0x3f7294f8,0xbea395c5,0x3f62241a,0xbeeff7fb,0x3fcbbbf8,0xbf9b02c6,0x3f2ff3e6,0xbf39f2ac,0x3f0f8784,0xbf53fac3,0x3ed6a399,0xbf686b39,
0x3f800000,0x0,0x3f7c187a,0xbe3228d4,0x3f708066,0xbeaf713a,0x3f5d924d,0xbf003a06,0x3fc3e200,0xbfa4d225,0x3f24381a,0xbf446337,0x3eff17b2,0xbf5df6be,0x3eadf73c,0xbf70c501,
0x3f800000,0x0,0x3f7b87b2,0xbe3e853e,0x3f6e46be,0xbebb31a0,0x3f58b3a1,0xbf084b92,0x3fbb8f3b,0xbfae3bde,0x3f17de12,0xbf4e1689,0x3eddbe79,0xbf66becc,0x3e840270,0xbf77583a,
0x3f800000,0x0,0x3f7aed37,0xbe4ada4f,0x3f6be858,0xbec6d529,0x3f5389c7,0xbf102dd5,0x3fb2c8c9,0xbfb73a23,0x3f0af1b7,0xbf570348,0x3ebb31a0,0xbf6e46be,0x3e3228d4,0xbf7c187a,
0x3f800000,0x0,0x3f7a4910,0xbe57278f,0x3f696591,0xbed25a09,0x3f4e1689,0xbf17de12,0x3fa99415,0xbfbfc767,0x3efafef7,0xbf5f20db,0x3e97a117,0xbf748422,0x3db5f8da,0xbf7efcc9,
0x3f800000,0x0,0x3f799b43,0xbe636c83,0x3f66becc,0xbeddbe79,0x3f485bca,0xbf1f599f,0x3f9ff6cb,0xbfc7de65,0x3edf28a9,0xbf666771,0x3e667c66,0xbf796e4e,0x3b490fc6,0xbf7fffb1,
0x3f800000,0x0,0x3f78e3d6,0xbe6fa8b2,0x3f63f473,0xbee900b7,0x3f425b89,0xbf269de3,0x3f95f6d9,0xbfcf7a1f,0x3ec27b55,0xbf6cd007,0x3e1c76de,0xbf7cfe73,0xbda973ba,0xbf7f1f49,
0x3f800000,0x0,0x3f7822d1,0xbe7bdba4,0x3f6106f2,0xbef41f07,0x3f3c17d9,0xbf2da859,0x3f8b9a6b,0xbfd695e5,0x3ea5129f,0xbf725470,0x3da3308c,0xbf7f2f9d,0xbe2bf804,0xbf7c5d3a,
0x3f800000,0x0,0x3f77583a,0xbe840270,0x3f5df6be,0xbeff17b2,0x3f3592e7,0xbf34768f,0x3f80e7e4,0xbfdd2d53,0x3e870ada,0xbf76ef5b,0x3bc90f88,0xbf7ffec4,0xbe80f8c0,0xbf77beb7,
0x3f800000,0x0,0x3f76841b,0xbe8a11f7,0x3f5ac450,0xbf04f484,0x3f2ecef7,0xbf3b0629,0x3f6bcbbb,0xbfe33c5a,0x3e5101f1,0xbf7a9c59,0xbd8a200a,0xbf7f6ac7,0xbeab0201,0xbf714c7a,
0x3f800000,0x0,0x3f75a67b,0xbe901c2c,0x3f577026,0xbf0a48ad,0x3f27ce61,0xbf4154e1,0x3f553641,0xbfe8bf3c,0x3e1324ca,0xbf7d57de,0xbe1008b7,0xbf7d7474,0xbed3c867,0xbf6912ae,
0x3f800000,0x0,0x3f74bf62,0xbe9620d2,0x3f53fac3,0xbf0f8784,0x3f209393,0xbf476085,0x3f3e1d4a,0xbfedb293,0x3da973ba,0xbf7f1f49,0xbe5a3997,0xbf7a1e84,0xbefafef7,0xbf5f20db,
0x3f800000,0x0,0x3f73ced9,0xbe9c1faf,0x3f5064af,0xbf14b039,0x3f19210f,0xbf4d26fd,0x3f268f12,0xbff21352,0x3cafea69,0xbf7ff0e3,0xbe919ddd,0xbf756d97,0xbf102dd5,0xbf5389c7,
0x3f800000,0x0,0x3f72d4eb,0xbea21887,0x3f4cae79,0xbf19c200,0x3f11796b,0xbf52a649,0x3f0e9a22,0xbff5dec6,0xbd2351cb,0xbf7fcbe2,0xbeb554ec,0xbf6f6830,0xbf21cbfb,0xbf466354,
0x3f800000,0x0,0x3f71d19f,0xbea80b1f,0x3f48d8b3,0xbf1ebc12,0x3f099f4e,0xbf57dc7f,0x3eec9a7f,0xbff91298,0xbdcefdb7,0xbf7eb069,0xbed8106b,0xbf6816a8,0xbf3238aa,0xbf37c655,
0x3f800000,0x0,0x3f70c501,0xbeadf73c,0x3f44e3f5,0xbf239da9,0x3f019573,0xbf5cc7d1,0x3ebb6ecf,0xbffbaccd,0xbe25c58c,0xbf7c9f8a,0xbef9a02d,0xbf5f8327,0xbf4154e1,0xbf27ce61,
0x3f800000,0x0,0x3f6faf1b,0xbeb3dca5,0x3f40d0da,0xbf286605,0x3ef2bd43,0xbf61668a,0x3e89cf86,0xbffdabcc,0xbe636c83,0xbf799b43,0xbf0cead0,0xbf55b993,0xbf4f0417,0xbf16999f,
0x3f800000,0x0,0x3f6e8ff8,0xbeb9bb1e,0x3f3ca003,0xbf2d1469,0x3ee1fb6a,0xbf65b710,0x3e2fb680,0xbfff0e58,0xbe901c2c,0xbf75a67b,0xbf1c420c,0xbf4ac77f,0xbf5b2c79,0xbf044889,
0x3f800000,0x0,0x3f6d67a1,0xbebf926f,0x3f385216,0xbf31a81d,0x3ed0eb2a,0xbf69b7e4,0x3d96c32c,0xbfffd397,0xbeadf73c,0xbf70c501,0xbf2ac082,0xbf3ebc1b,0xbf65b710,0xbee1fb6a,
0x3f800000,0x0,0x3f7ffec4,0xbbc90f88,0x3f7ffb11,0xbc490e90,0x3f7ff4e6,0xbc96c9b6,0x3fffec43,0xbd490ab0,0x3f7fe129,0xbcfb49ba,0x3f7fd397,0xbd16c32c,0x3f7fc38f,0xbd2fe007,
0x3f800000,0x0,0x3f7ff4e6,0xbc96c9b6,0x3f7fd397,0xbd16c32c,0x3f7f9c18,0xbd621469,0x3fff4e6d,0xbe16a905,0x3f7eea9d,0xbdbc3ac3,0x3f7e70b0,0xbde1bc2e,0x3f7de0b1,0xbe039502,
0x3f800000,0x0,0x3f7fe129,0xbcfb49ba,0x3f7f84ab,0xbd7b2b74,0x3f7eea9d,0xbdbc3ac3,0x3ffe1324,0xbe7ab273,0x3f7cfe73,0xbe1c76de,0x3f7baccd,0xbe3b6ecf,0x3f7a1e84,0xbe5a3997,
0x3f800000,0x0,0x3f7fc38f,0xbd2fe007,0x3f7f0e58,0xbdafb680,0x3f7de0b1,0xbe039502,0x3ffc3b28,0xbeaf10a2,0x3f7a1e84,0xbe5a3997,0x3f778bc5,0xbe827dc0,0x3f748422,0xbe97a117,
0x3f800000,0x0,0x3f7f9c18,0xbd621469,0x3f7e70b0,0xbde1bc2e,0x3f7c7eb0,0xbe28defc,0x3ff9c79d,0xbee05c13,0x3f764d97,0xbe8b9507,0x3f721352,0xbea68f12,0x3f6d1c1d,0xbec1071e,
0x3f800000,0x0,0x3f7f6ac7,0xbd8a200a,0x3f7dabcc,0xbe09cf86,0x3f7ac516,0xbe4dee60,0x3ff6ba07,0xbf088e93,0x3f718f57,0xbea986c4,0x3f6b4b0c,0xbec9b953,0x3f63f473,0xbee900b7,
0x3f800000,0x0,0x3f7f2f9d,0xbda3308c,0x3f7cbfc9,0xbe22abb6,0x3f78b47b,0xbe72b651,0x3ff31447,0xbf209ae5,0x3f6be858,0xbec6d529,0x3f633c5a,0xbeebcbbb,0x3f591e6a,0xbf07a136,
0x3f800000,0x0,0x3f7eea9d,0xbdbc3ac3,0x3f7baccd,0xbe3b6ecf,0x3f764d97,0xbe8b9507,0x3feed89e,0xbf38442a,0x3f655e0b,0xbee363fa,0x3f59f26a,0xbf064b82,0x3f4cae79,0xbf19c200,
0x3f800000,0x0,0x3f7e9bc9,0xbdd53db9,0x3f7a7302,0xbe541501,0x3f73913f,0xbe9d9e78,0x3fea09a7,0xbf4f7bca,0x3f5df6be,0xbeff17b2,0x3f4f7a1f,0xbf15f6d9,0x3f3ebc1b,0xbf2ac082,
0x3f800000,0x0,0x3f7e4323,0xbdee3876,0x3f791298,0xbe6c9a7f,0x3f708066,0xbeaf713a,0x3fe4aa59,0xbf663375,0x3f55b993,0xbf0cead0,0x3f43e200,0xbf24d225,0x3f2f61a5,0xbf3a7ca4,
0x3f800000,0x0,0x3f7de0b1,0xbe039502,0x3f778bc5,0xbe827dc0,0x3f6d1c1d,0xbec1071e,0x3fdebe05,0xbf7c5d27,0x3f4cae79,0xbf19c200,0x3f373a23,0xbf32c8c9,0x3f1ebc12,0xbf48d8b3,
0x3f800000,0x0,0x3f7d7474,0xbe1008b7,0x3f75dec6,0xbe8e9a22,0x3f696591,0xbed25a09,0x3fd84853,0xbf88f59b,0x3f42de29,0xbf26050a,0x3f299415,0xbf3fc767,0x3f0cead0,0xbf55b993,
0x3f800000,0x0,0x3f7cfe73,0xbe1c76de,0x3f740bdd,0xbe9aa086,0x3f655e0b,0xbee363fa,0x3fd14d3d,0xbf93682a,0x3f385216,0xbf31a81d,0x3f1b02c6,0xbf4bbbf8,0x3ef41f07,0xbf6106f2,
0x3f800000,0x0,0x3f7c7eb0,0xbe28defc,0x3f721352,0xbea68f12,0x3f6106f2,0xbef41f07,0x3fc9d112,0xbf9d7fd1,0x3f2d1469,0xbf3ca003,0x3f0b9a6b,0xbf5695e5,0x3ecc9b8b,0xbf6aab7b,
0x3f800000,0x0,0x3f7bf531,0xbe354098,0x3f6ff573,0xbeb263ef,0x3f5c61c7,0xbf0242b1,0x3fc1d870,0xbfa73656,0x3f212ff9,0xbf46e22a,0x3ef6e0cb,0xbf604621,0x3ea395c5,0xbf7294f8,
0x3f800000,0x0,0x3f7b61fc,0xbe419b37,0x3f6db293,0xbebe1d4a,0x3f577026,0xbf0a48ad,0x3fb96842,0xbfb085bb,0x3f14b039,0xbf5064af,0x3ed53641,0xbf68bf3c,0x3e72b651,0xbf78b47b,
0x3f800000,0x0,0x3f7ac516,0xbe4dee60,0x3f6b4b0c,0xbec9b953,0x3f5233c6,0xbf121eb0,0x3fb085bb,0xbfb96842,0x3f07a136,0xbf591e6a,0x3eb263ef,0xbf6ff573,0x3e1c76de,0xbf7cfe73,
0x3f800000,0x0,0x3f7a1e84,0xbe5a3997,0x3f68bf3c,0xbed53641,0x3f4cae79,0xbf19c200,0x3fa73656,0xbfc1d870,0x3ef41f07,0xbf6106f2,0x3e8e9a22,0xbf75dec6,0x3d8a200a,0xbf7f6ac7,
0x3f800000,0x0,0x3f796e4e,0xbe667c66,0x3f660f88,0xbee0924f,0x3f46e22a,0xbf212ff9,0x3f9d7fd1,0xbfc9d112,0x3ed8106b,0xbf6816a8,0x3e541501,0xbf7a7302,0xbc96c9b6,0xbf7ff4e6,
0x3f800000,0x0,0x3f78b47b,0xbe72b651,0x3f633c5a,0xbeebcbbb,0x3f40d0da,0xbf286605,0x3f93682a,0xbfd14d3d,0x3ebb31a0,0xbf6e46be,0x3e09cf86,0xbf7dabcc,0xbdd53db9,0xbf7e9bc9,
0x3f800000,0x0,0x3f77f110,0xbe7ee6e1,0x3f604621,0xbef6e0cb,0x3f3a7ca4,0xbf2f61a5,0x3f88f59b,0xbfd84853,0x3e9d9e78,0xbf73913f,0x3d7b2b74,0xbf7f84ab,0xbe419b37,0xbf7b61fc,
0x3f800000,0x0,0x3f772417,0xbe8586ce,0x3f5d2d53,0xbf00e7e4,0x3f33e7bc,0xbf36206c,0x3f7c5d27,0xbfdebe05,0x3e7ee6e1,0xbf77f110,0xbc490e90,0xbf7ffb11,0xbe8b9507,0xbf764d97,
0x3f800000,0x0,0x3f764d97,0xbe8b9507,0x3f59f26a,0xbf064b82,0x3f2d1469,0xbf3ca003,0x3f663375,0xbfe4aa59,0x3e419b37,0xbf7b61fc,0xbdafb680,0xbf7f0e58,0xbeb554ec,0xbf6f6830,
0x3f800000,0x0,0x3f756d97,0xbe919ddd,0x3f5695e5,0xbf0b9a6b,0x3f26050a,0xbf42de29,0x3f4f7bca,0xbfea09a7,0x3e039502,0xbf7de0b1,0xbe22abb6,0xbf7cbfc9,0xbeddbe79,0xbf66becc,
0x3f800000,0x0,0x3f748422,0xbe97a117,0x3f531849,0xbf10d3cd,0x3f1ebc12,0xbf48d8b3,0x3f38442a,0xbfeed89e,0x3d8a200a,0xbf7f6ac7,0xbe6c9a7f,0xbf791298,0xbf0242b1,0xbf5c61c7,
0x3f800000,0x0,0x3f73913f,0xbe9d9e78,0x3f4f7a1f,0xbf15f6d9,0x3f173c07,0xbf4e8d90,0x3f209ae5,0xbff31447,0x3bc90f88,0xbf7ffec4,0xbe9aa086,0xbf740bdd,0xbf14b039,0xbf5064af,
0x3f800000,0x0,0x3f7294f8,0xbea395c5,0x3f4bbbf8,0xbf1b02c6,0x3f0f8784,0xbf53fac3,0x3f088e93,0xbff6ba07,0xbd621469,0xbf7f9c18,0xbebe1d4a,0xbf6db293,0xbf26050a,0xbf42de29,
0x3f800000,0x0,0x3f718f57,0xbea986c4,0x3f47de65,0xbf1ff6cb,0x3f07a136,0xbf591e6a,0x3ee05c13,0xbff9c79d,0xbdee3876,0xbf7e4323,0xbee0924f,0xbf660f88,0xbf36206c,0xbf33e7bc,
0x3f800000,0x0,0x3f708066,0xbeaf713a,0x3f43e200,0xbf24d225,0x3eff17b2,0xbf5df6be,0x3eaf10a2,0xbffc3b28,0xbe354098,0xbf7bf531,0xbf00e7e4,0xbf5d2d53,0xbf44e3f5,0xbf239da9,
0x3f800000,0x0,0x3f6f6830,0xbeb554ec,0x3f3fc767,0xbf299415,0x3eee9479,0xbf628210,0x3e7ab273,0xbffe1324,0xbe72b651,0xbf78b47b,0xbf10d3cd,0xbf531849,0xbf5233c6,0xbf121eb0,
0x3f800000,0x0,0x3f6e46be,0xbebb31a0,0x3f3b8f3b,0xbf2e3bde,0x3eddbe79,0xbf66becc,0x3e16a905,0xbfff4e6d,0xbe97a117,0xbf748422,0xbf1ff6cb,0xbf47de65,0xbf5df6be,0xbeff17b2,
0x3f800000,0x0,0x3f6d1c1d,0xbec1071e,0x3f373a23,0xbf32c8c9,0x3ecc9b8b,0xbf6aab7b,0x3d490ab0,0xbfffec43,0xbeb554ec,0xbf6f6830,0xbf2e3bde,0xbf3b8f3b,0xbf6816a8,0xbed8106b,
0x3f800000,0x0,0x3f7ffd39,0xbc16cb58,0x3f7ff4e6,0xbc96c9b6,0x3f7fe705,0xbce22a7a,0x3fffd397,0xbd96c32c,0x3f7fba9e,0xbd3c6dd5,0x3f7f9c18,0xbd621469,0x3f7f7808,0xbd83db0a,
0x3f800000,0x0,0x3f7ff0e3,0xbcafea69,0x3f7fc38f,0xbd2fe007,0x3f7f7808,0xbd83db0a,0x3fff0e58,0xbe2fb680,0x3f7e868b,0xbddb7d37,0x3f7de0b1,0xbe039502,0x3f7d1cdd,0xbe195be0,
0x3f800000,0x0,0x3f7fdaaf,0xbd0a342f,0x3f7f6ac7,0xbd8a200a,0x3f7eb069,0xbdcefdb7,0x3ffdabcc,0xbe89cf86,0x3f7c5d3a,0xbe2bf804,0x3f7ac516,0xbe4dee60,0x3f78e3d6,0xbe6fa8b2,
0x3f800000,0x0,0x3f7fba9e,0xbd3c6dd5,0x3f7eea9d,0xbdbc3ac3,0x3f7d906e,0xbe0cec4a,0x3ffbaccd,0xbebb6ecf,0x3f7940c0,0xbe698bba,0x3f764d97,0xbe8b9507,0x3f72d4eb,0xbea21887,
0x3f800000,0x0,0x3f7f90b1,0xbd6ea038,0x3f7e4323,0xbdee3876,0x3f7c187a,0xbe3228d4,0x3ff91298,0xbeec9a7f,0x3f75341d,0xbe931f35,0x3f708066,0xbeaf713a,0x3f6afb8c,0xbecb2aae,
0x3f800000,0x0,0x3f7f5ce9,0xbd9064b4,0x3f7d7474,0xbe1008b7,0x3f7a4910,0xbe57278f,0x3ff5dec6,0xbf0e9a22,0x3f703b37,0xbeb0eacb,0x3f696591,0xbed25a09,0x3f61668a,0xbef2bd43,
0x3f800000,0x0,0x3f7f1f49,0xbda973ba,0x3f7c7eb0,0xbe28defc,0x3f7822d1,0xbe7bdba4,0x3ff21352,0xbf268f12,0x3f6a5ad9,0xbece0bea,0x3f6106f2,0xbef41f07,0x3f5627fe,0xbf0c42c9,
0x3f800000,0x0,0x3f7ed7d4,0xbdc27c39,0x3f7b61fc,0xbe419b37,0x3f75a67b,0xbe901c2c,0x3fedb293,0xbf3e1d4a,0x3f6398ac,0xbeea6681,0x3f577026,0xbf0a48ad,0x3f495521,0xbf1e1e22,
0x3f800000,0x0,0x3f7e868b,0xbddb7d37,0x3f7a1e84,0xbe5a3997,0x3f72d4eb,0xbea21887,0x3fe8bf3c,0xbf553641,0x3f5bfb34,0xbf02ef9f,0x3f4cae79,0xbf19c200,0x3f3b0629,0xbf2ecef7,
0x3f800000,0x0,0x3f7e2b72,0xbdf475c0,0x3f78b47b,0xbe72b651,0x3f6faf1b,0xbeb3dca5,0x3fe33c5a,0xbf6bcbbb,0x3f5389c7,0xbf102dd5,0x3f40d0da,0xbf286605,0x3f2b561b,0xbf3e35c5,
0x3f800000,0x0,0x3f7dc68c,0xbe06b26e,0x3f772417,0xbe8586ce,0x3f6c3624,0xbec5625c,0x3fdd2d53,0xbf80e7e4,0x3f4a4c87,0xbf1ce11f,0x3f33e7bc,0xbf36206c,0x3f1a6293,0xbf4c3578,
0x3f800000,0x0,0x3f7d57de,0xbe1324ca,0x3f756d97,0xbe919ddd,0x3f686b39,0xbed6a399,0x3fd695e5,0xbf8b9a6b,0x3f404c5c,0xbf28fd41,0x3f26050a,0xbf42de29,0x3f084b92,0xbf58b3a1,
0x3f800000,0x0,0x3f7cdf6c,0xbe1f917b,0x3f73913f,0xbe9d9e78,0x3f644fac,0xbee79a5d,0x3fcf7a1f,0xbf95f6d9,0x3f3592e7,0xbf34768f,0x3f173c07,0xbf4e8d90,0x3eea6681,0xbf6398ac,
0x3f800000,0x0,0x3f7c5d3a,0xbe2bf804,0x3f718f57,0xbea986c4,0x3f5fe4e9,0xbef840c8,0x3fc7de65,0xbf9ff6cb,0x3f2a2a80,0xbf3f41fc,0x3f07a136,0xbf591e6a,0x3ec27b55,0xbf6cd007,
0x3f800000,0x0,0x3f7bd14d,0xbe3857ec,0x3f6f6830,0xbeb554ec,0x3f5b2c79,0xbf044889,0x3fbfc767,0xbfa99415,0x3f1e1e22,0xbf495521,0x3eee9479,0xbf628210,0x3e9920fe,0xbf74484b,
0x3f800000,0x0,0x3f7b3bab,0xbe44b0b9,0x3f6d1c1d,0xbec1071e,0x3f5627fe,0xbf0c42c9,0x3fb73a23,0xbfb2c8c9,0x3f11796b,0xbf52a649,0x3ecc9b8b,0xbf6aab7b,0x3e5d4b1a,0xbf79f35e,
0x3f800000,0x0,0x3f7a9c59,0xbe5101f1,0x3f6aab7b,0xbecc9b8b,0x3f50d937,0xbf140c5f,0x3fae3bde,0xbfbb8f3b,0x3f044889,0xbf5b2c79,0x3ea986c4,0xbf718f57,0x3e06b26e,0xbf7dc68c,
0x3f800000,0x0,0x3f79f35e,0xbe5d4b1a,0x3f6816a8,0xbed8106b,0x3f4b41fa,0xbf1ba299,0x3fa4d225,0xbfc3e200,0x3eed3063,0xbf62df7b,0x3e8586ce,0xbf772417,0x3d3c6dd5,0xbf7fba9e,
0x3f800000,0x0,0x3f7940c0,0xbe698bba,0x3f655e0b,0xbee363fa,0x3f456439,0xbf2302d3,0x3f9b02c6,0xbfcbbbf8,0x3ed0eb2a,0xbf69b7e4,0x3e419b37,0xbf7b61fc,0xbd2351cb,0xbf7fcbe2,
0x3f800000,0x0,0x3f788486,0xbe75c35a,0x3f628210,0xbeee9479,0x3f3f41fc,0xbf2a2a80,0x3f90d3cd,0xbfd31849,0x3eb3dca5,0xbf6faf1b,0x3dee3876,0xbf7e4323,0xbe007745,0xbf7dfa38,
0x3f800000,0x0,0x3f77beb7,0xbe80f8c0,0x3f5f8327,0xbef9a02d,0x3f38dd65,0xbf311722,0x3f864b82,0xbfd9f26a,0x3e9620d2,0xbf74bf62,0x3d2fe007,0xbf7fc38f,0xbe57278f,0xbf7a4910,
0x3f800000,0x0,0x3f76ef5b,0xbe870ada,0x3f5c61c7,0xbf0242b1,0x3f3238aa,0xbf37c655,0x3f76e0cb,0xbfe04621,0x3e6fa8b2,0xbf78e3d6,0xbcfb49ba,0xbf7fe129,0xbe9620d2,0xbf74bf62,
0x3f800000,0x0,0x3f76167a,0xbe8d17c0,0x3f591e6a,0xbf07a136,0x3f2b561b,0xbf3e35c5,0x3f60924f,0xbfe60f88,0x3e3228d4,0xbf7c187a,0xbdd53db9,0xbf7e9bc9,0xbebf926f,0xbf6d67a1,
0x3f800000,0x0,0x3f75341d,0xbe931f35,0x3f55b993,0xbf0cead0,0x3f24381a,0xbf446337,0x3f49b953,0xbfeb4b0c,0x3de7fa9a,0xbf7e5a38,0xbe354098,0xbf7bf531,0xbee79a5d,0xbf644fac,
0x3f800000,0x0,0x3f74484b,0xbe9920fe,0x3f5233c6,0xbf121eb0,0x3f1ce11f,0xbf4a4c87,0x3f3263ef,0xbfeff573,0x3d55880e,0xbf7fa6e3,0xbe7ee6e1,0xbf77f110,0xbf06f686,0xbf5988ad,
0x3f800000,0x0,0x3f73530e,0xbe9f1cdf,0x3f4e8d90,0xbf173c07,0x3f1553b7,0xbf4fefa8,0x3f1aa086,0xbff40bdd,0xbc16cb58,0xbf7ffd39,0xbea395c5,0xbf7294f8,0xbf19210f,0xbf4d26fd,
0x3f800000,0x0,0x3f725470,0xbea5129f,0x3f4ac77f,0xbf1c420c,0x3f0d9281,0xbf554aa4,0x3f027dc0,0xbff78bc5,0xbd9064b4,0xbf7f5ce9,0xbec6d529,0xbf6be858,0xbf2a2a80,0xbf3f41fc,
0x3f800000,0x0,0x3f714c7a,0xbeab0201,0x3f46e22a,0xbf212ff9,0x3f05a02c,0xbf5a5ba0,0x3ed41501,0xbffa7302,0xbe06b26e,0xbf7dc68c,0xbee900b7,0xbf63f473,0xbf39f2ac,0xbf2ff3e6,
0x3f800000,0x0,0x3f703b37,0xbeb0eacb,0x3f42de29,0xbf26050a,0x3efafef7,0xbf5f20db,0x3ea2abb6,0xbffcbfc9,0xbe44b0b9,0xbf7b3bab,0xbf04f484,0xbf5ac450,0xbf485bca,0xbf1f599f,
0x3f800000,0x0,0x3f6f20b0,0xbeb6ccc3,0x3f3ebc1b,0xbf2ac082,0x3eea6681,0xbf6398ac,0x3e61bc2e,0xbffe70b0,0xbe80f8c0,0xbf77beb7,0xbf14b039,0xbf5064af,0xbf554aa4,0xbf0d9281,
0x3f800000,0x0,0x3f6dfcf2,0xbebca7af,0x3f3a7ca4,0xbf2f61a5,0x3ed97cb9,0xbf67c187,0x3dfb2b74,0xbfff84ab,0xbe9f1cdf,0xbf73530e,0xbf239da9,0xbf44e3f5,0xbf60a6cf,0xbef58035,
0x3f800000,0x0,0x3f6cd007,0xbec27b55,0x3f36206c,0xbf33e7bc,0x3ec8477c,0xbf6b99fb,0x3cc90e90,0xbffffb11,0xbebca7af,0xbf6dfcf2,0xbf31a81d,0xbf385216,0xbf6a5ad9,0xbece0bea,
0x3f800000,0x0,0x0,0x0,0x0,0x0,0x0,0x0,0x0,0x0,0x0,0x0,0x0,0x0,0x0,0x0,
0x0,0x0,0x0,0x0,0x0,0x0,0x0,0x0,0x0,0x0,0x0,0x0,0x0,0x0,0x0,0x0,
0x0,0x0,0x3e000000,0xbf20dff7,0x3ed0c429,0x0,0x3e000000,0x3e61f78b,0x3e0a8bd4,0x0,0x3e000000,0x3d5413cd,0x3d5df9ad,0x0,0x3e000000,0x3cf043ab,
0x0,0x0,0x3e000000,0x3ccbafaf,0xbd5df9ad,0x0,0x3e000000,0x3cf043ab,0xbe0a8bd4,0x0,0x3e000000,0x3d5413cd,0xbed0c429,0x0,0x3e000000,0x3e61f78b,
0x0,0x0,0x0,0x0,0x3f000000,0x0,0x0,0x3f000000,0x0,0x0,0x0,0x0,0x0,0x0,0x0,0x0,
0x0,0x0,0x0,0x0,0x0,0x0,0x0,0x0,0x0,0x0,0x0,0x0,0x3f000000,0x0,0x0,0xbf000000,
0x0,0x0,0x3e000000,0xbe3f90c7,0xbe8b7e3f,0x0,0x3e000000,0xbeb641af,0x3ea73d75,0x0,0x3e000000,0x3e9a827a,0x3da61ad1,0x0,0x3e000000,0x3dd906bd,
0x0,0x0,0x3e000000,0x3dab0dc1,0xbda61ad1,0x0,0x3e000000,0x3dd906bd,0xbea73d75,0x0,0x3e000000,0x3e9a827a,0x3e8b7e3f,0x0,0x3e000000,0xbeb641af,
0x0,0x0,0x0,0x0,0x0,0x0,0x0,0x0,0x3f000000,0x0,0x0,0x3f000000,0x0,0x0,0x0,0x0,
0x0,0x0,0x0,0x0,0x0,0x0,0x0,0x0,0x3f000000,0x0,0x0,0xbf000000,0x0,0x0,0x0,0x0,
0x0,0x0,0x3e000000,0xbdab0dc1,0xbda61ad1,0x0,0x3e000000,0xbdd906bd,0xbea73d75,0x0,0x3e000000,0xbe9a827a,0x3e8b7e3f,0x0,0x3e000000,0x3eb641af,
0x0,0x0,0x3e000000,0x3e3f90c7,0xbe8b7e3f,0x0,0x3e000000,0x3eb641af,0x3ea73d75,0x0,0x3e000000,0xbe9a827a,0x3da61ad1,0x0,0x3e000000,0xbdd906bd,
0x0,0x0,0x0,0x0,0x0,0x0,0x0,0x0,0x0,0x0,0x0,0x0,0x3f000000,0x0,0x0,0x3f000000,
0x0,0x0,0x0,0x0,0x3f000000,0x0,0x0,0xbf000000,0x0,0x0,0x0,0x0,0x0,0x0,0x0,0x0,
0x0,0x0,0x3e000000,0xbccbafaf,0xbd5df9ad,0x0,0x3e000000,0xbcf043ab,0xbe0a8bd4,0x0,0x3e000000,0xbd5413cd,0xbed0c429,0x0,0x3e000000,0xbe61f78b,
0x0,0x0,0x3e000000,0x3f20dff7,0x3ed0c429,0x0,0x3e000000,0xbe61f78b,0x3e0a8bd4,0x0,0x3e000000,0xbd5413cd,0x3d5df9ad,0x0,0x3e000000,0xbcf043ab,
};

struct Params {
    const __nv_bfloat16 *wr, *wi, *lre, *lim, *ldt, *dsk;
    float* out;
};

struct cf { float x, y; };
#define YIELD() asm volatile("pmevent 1;")
#define YS 14
#define YIELD_S1() do { if (YS & 1) YIELD(); } while (0)
#define YIELD_S2() do { if (YS & 2) YIELD(); } while (0)
#define YIELD_S3() do { if (YS & 4) YIELD(); } while (0)
__device__ __forceinline__ uint32_t smem_u32(const void* p) { return (uint32_t)__cvta_generic_to_shared(p); }
__device__ __forceinline__ void mbar_init(uint32_t a, uint32_t c) { asm volatile("mbarrier.init.shared::cta.b64 [%0], %1;" ::"r"(a), "r"(c) : "memory"); }
__device__ __forceinline__ void mbar_expect_tx(uint32_t a, uint32_t b) { asm volatile("mbarrier.arrive.expect_tx.shared::cta.b64 _, [%0], %1;" ::"r"(a), "r"(b) : "memory"); }
__device__ __forceinline__ void mbar_arrive(uint32_t a) { asm volatile("mbarrier.arrive.shared::cta.b64 _, [%0];" ::"r"(a) : "memory"); }
__device__ __forceinline__ void warp_arrive(uint32_t a) {
    __syncwarp();
    asm volatile("{.reg .pred p; elect.sync _|p, 0xffffffff; @p mbarrier.arrive.shared::cta.b64 _, [%0];}" ::"r"(a) : "memory");
}
__device__ __forceinline__ uint32_t mbar_try(uint32_t a, uint32_t ph) {
    uint32_t ok;
    asm volatile("{.reg .pred p; mbarrier.try_wait.parity.shared::cta.b64 p, [%1], %2; selp.u32 %0, 1, 0, p;}" : "=r"(ok) : "r"(a), "r"(ph) : "memory");
    return ok;
}
__device__ __forceinline__ void mbar_wait(uint32_t a, uint32_t ph) {
    uint32_t ok, n = 0;
    do { ok = mbar_try(a, ph); } while (!ok && ++n < SPIN_LIMIT);
}
__device__ __forceinline__ void mbar_wait_fast(uint32_t a, uint32_t ph) { if (!mbar_try(a, ph)) mbar_wait(a, ph); }
__device__ __forceinline__ unsigned ld_rlx(const unsigned* p) { unsigned v; asm volatile("ld.relaxed.gpu.global.u32 %0, [%1];" : "=r"(v) : "l"(p) : "memory"); return v; }
__device__ __forceinline__ void wait_cnt(const unsigned* p, unsigned target) {
    unsigned n = 0;
    while ((int)(ld_rlx(p) - target) < 0 && ++n < SPIN_LIMIT) __nanosleep(20);
}
__device__ __forceinline__ void red_hint(unsigned* p) { asm volatile("red.relaxed.gpu.global.add.u32 [%0], 1;" ::"l"(p) : "memory"); }
__device__ __forceinline__ void fence_async() { asm volatile("fence.proxy.async.global;" ::: "memory"); }
__device__ __forceinline__ void fence_async_sm() { asm volatile("fence.proxy.async.shared::cta;" ::: "memory"); }
#define bar_sync(id, n) asm volatile("bar.sync %0, %1;" ::"n"(id), "n"(n) : "memory")
#define bar_arrive(id, n) asm volatile("bar.arrive %0, %1;" ::"n"(id), "n"(n) : "memory")
__device__ __forceinline__ bool elect_one() {
    uint32_t r;
    asm volatile("{.reg .pred p; elect.sync _|p, 0xffffffff; selp.u32 %0, 1, 0, p;}" : "=r"(r));
    return r != 0;
}

__device__ __forceinline__ void tma2d(uint32_t dst, const CUtensorMap* m, int c0, int c1, uint32_t bar) {
    asm volatile("cp.async.bulk.tensor.2d.shared::cluster.global.mbarrier::complete_tx::bytes [%0], [%1, {%3,%4}], [%2];" ::"r"(dst), "l"(m), "r"(bar), "r"(c0), "r"(c1) : "memory");
}
__device__ __forceinline__ void tma3d(uint32_t dst, const CUtensorMap* m, int c0, int c1, int c2, uint32_t bar) {
    asm volatile("cp.async.bulk.tensor.3d.shared::cluster.global.mbarrier::complete_tx::bytes [%0], [%1, {%3,%4,%5}], [%2];" ::"r"(dst), "l"(m), "r"(bar), "r"(c0), "r"(c1), "r"(c2) : "memory");
}
__device__ __forceinline__ void tma2d_mc(uint32_t dst, const CUtensorMap* m, int c0, int c1, uint32_t bar) {
    asm volatile("cp.async.bulk.tensor.2d.shared::cluster.global.mbarrier::complete_tx::bytes.multicast::cluster [%0], [%1, {%3,%4}], [%2], %5;" ::"r"(dst), "l"(m), "r"(bar), "r"(c0), "r"(c1), "h"((uint16_t)3) : "memory");
}
__device__ __forceinline__ void tma4d_mc(uint32_t dst, const CUtensorMap* m, int c0, int c1, int c2, int c3, uint32_t bar) {
    asm volatile("cp.async.bulk.tensor.4d.shared::cluster.global.mbarrier::complete_tx::bytes.multicast::cluster [%0], [%1, {%3,%4,%5,%6}], [%2], %7;" ::"r"(dst), "l"(m), "r"(bar), "r"(c0), "r"(c1), "r"(c2), "r"(c3), "h"((uint16_t)3) : "memory");
}
__device__ __forceinline__ void tma4d(uint32_t dst, const CUtensorMap* m, int c0, int c1, int c2, int c3, uint32_t bar) {
    asm volatile("cp.async.bulk.tensor.4d.shared::cluster.global.mbarrier::complete_tx::bytes [%0], [%1, {%3,%4,%5,%6}], [%2];" ::"r"(dst), "l"(m), "r"(bar), "r"(c0), "r"(c1), "r"(c2), "r"(c3) : "memory");
}
__device__ __forceinline__ void tma2d_st(const CUtensorMap* m, int c0, int c1, uint32_t src) {
    asm volatile("cp.async.bulk.tensor.2d.global.shared::cta.bulk_group [%0, {%2,%3}], [%1];" ::"l"(m), "r"(src), "r"(c0), "r"(c1) : "memory");
}
__device__ __forceinline__ void tma3d_st(const CUtensorMap* m, int c0, int c1, int c2, uint32_t src) {
    asm volatile("cp.async.bulk.tensor.3d.global.shared::cta.bulk_group [%0, {%2,%3,%4}], [%1];" ::"l"(m), "r"(src), "r"(c0), "r"(c1), "r"(c2) : "memory");
}
__device__ __forceinline__ void tma5d(uint32_t dst, const CUtensorMap* m, int c0, int c1, int c2, int c3, int c4, uint32_t bar) {
    asm volatile("cp.async.bulk.tensor.5d.shared::cluster.global.mbarrier::complete_tx::bytes [%0], [%1, {%3,%4,%5,%6,%7}], [%2];" ::"r"(dst), "l"(m), "r"(bar), "r"(c0), "r"(c1), "r"(c2), "r"(c3), "r"(c4) : "memory");
}
__device__ __forceinline__ void tma5d_mc(uint32_t dst, const CUtensorMap* m, int c0, int c1, int c2, int c3, int c4, uint32_t bar) {
    asm volatile("cp.async.bulk.tensor.5d.shared::cluster.global.mbarrier::complete_tx::bytes.multicast::cluster [%0], [%1, {%3,%4,%5,%6,%7}], [%2], %8;" ::"r"(dst), "l"(m), "r"(bar), "r"(c0), "r"(c1), "r"(c2), "r"(c3), "r"(c4), "h"((uint16_t)3) : "memory");
}
__device__ __forceinline__ void bulk_pf(const void* src, uint32_t n) { asm volatile("cp.async.bulk.prefetch.L2.global [%0], %1;" ::"l"(src), "r"(n) : "memory"); }
__device__ __forceinline__ void tma4d_pf(const CUtensorMap* m, int c0, int c1, int c2, int c3) {
    asm volatile("cp.async.bulk.prefetch.tensor.4d.L2.global [%0, {%1,%2,%3,%4}];" ::"l"(m), "r"(c0), "r"(c1), "r"(c2), "r"(c3) : "memory");
}
__device__ __forceinline__ void tma5d_pf(const CUtensorMap* m, int c0, int c1, int c2, int c3, int c4) {
    asm volatile("cp.async.bulk.prefetch.tensor.5d.L2.global [%0, {%1,%2,%3,%4,%5}];" ::"l"(m), "r"(c0), "r"(c1), "r"(c2), "r"(c3), "r"(c4) : "memory");
}
__device__ __forceinline__ void bulk_ld(uint32_t dst, const void* src, uint32_t n, uint32_t bar) {
    asm volatile("cp.async.bulk.shared::cluster.global.mbarrier::complete_tx::bytes [%0], [%1], %2, [%3];" ::"r"(dst), "l"(src), "r"(n), "r"(bar) : "memory");
}
__device__ __forceinline__ void bulk_st(void* dst, uint32_t src, uint32_t n) {
    asm volatile("cp.async.bulk.global.shared::cta.bulk_group [%0], [%1], %2;" ::"l"(dst), "r"(src), "r"(n) : "memory");
}
__device__ __forceinline__ void bulk_commit() { asm volatile("cp.async.bulk.commit_group;" ::: "memory"); }
__device__ __forceinline__ void bulk_wait_read() { asm volatile("cp.async.bulk.wait_group.read 0;" ::: "memory"); }
__device__ __forceinline__ void bulk_wait_all() { asm volatile("cp.async.bulk.wait_group 0;" ::: "memory"); }
__device__ __forceinline__ void stsm4(uint32_t a, uint32_t r0, uint32_t r1, uint32_t r2, uint32_t r3) {
    asm volatile("stmatrix.sync.aligned.m8n8.x4.shared.b16 [%0], {%1,%2,%3,%4};" ::"r"(a), "r"(r0), "r"(r1), "r"(r2), "r"(r3) : "memory");
}
__device__ __forceinline__ void sts128(uint32_t a, uint32_t r0, uint32_t r1, uint32_t r2, uint32_t r3) {
    asm volatile("st.shared.v4.b32 [%0], {%1,%2,%3,%4};" ::"r"(a), "r"(r0), "r"(r1), "r"(r2), "r"(r3) : "memory");
}
__device__ __forceinline__ void lds128f(uint32_t a, float& x, float& y, float& z, float& u) { asm volatile("ld.shared.v4.f32 {%0,%1,%2,%3}, [%4];" : "=f"(x), "=f"(y), "=f"(z), "=f"(u) : "r"(a) : "memory"); }
__device__ __forceinline__ cf lds_cf(uint32_t a) { cf v; asm volatile("ld.shared.v2.f32 {%0,%1}, [%2];" : "=f"(v.x), "=f"(v.y) : "r"(a) : "memory"); return v; }
__device__ __forceinline__ void stg128(const void* a, uint32_t r0, uint32_t r1, uint32_t r2, uint32_t r3) {
    asm volatile("st.global.v4.b32 [%0], {%1,%2,%3,%4};" ::"l"(a), "r"(r0), "r"(r1), "r"(r2), "r"(r3) : "memory");
}
__device__ __forceinline__ int fresh_lane() { int v; asm volatile("mov.u32 %0, %%laneid;" : "=r"(v)); return v; }
__device__ __forceinline__ uint32_t opaque32(uint32_t v) { asm volatile("" : "+r"(v)); return v; }
__device__ __forceinline__ const uint8_t* padd(const void* base, uint32_t off) {
    uint64_t r;
    asm("{.reg .u32 l, h; mov.b64 {l, h}, %1; add.cc.u32 l, l, %2; addc.u32 h, h, 0; mov.b64 %0, {l, h};}" : "=l"(r) : "l"(base), "r"(off));
    return (const uint8_t*)r;
}
template <int N, int STRIDE> __device__ __forceinline__ void ldtab(uint32_t (&v)[4 * N], uint32_t off) {
    const uint8_t* a = padd(g_tab, off);
#pragma unroll
    for (int i = 0; i < N; i++)
        asm volatile("ld.global.nc.v4.b32 {%0,%1,%2,%3}, [%4];" : "=r"(v[4 * i]), "=r"(v[4 * i + 1]), "=r"(v[4 * i + 2]), "=r"(v[4 * i + 3]) : "l"(a + i * STRIDE));
}
template <int STRIDE> __device__ __forceinline__ void ldtab_cf(cf (&t)[8], uint32_t off) {
    uint32_t v[16];
    ldtab<4, STRIDE>(v, off);
#pragma unroll
    for (int i = 0; i < 8; i++) t[i] = {__uint_as_float(v[2 * i]), __uint_as_float(v[2 * i + 1])};
}
__device__ __forceinline__ uint32_t lds16(uint32_t a) { uint32_t v; asm volatile("ld.shared.u16 %0, [%1];" : "=r"(v) : "r"(a)); return v; }
__device__ __forceinline__ unsigned get_epoch(uint32_t bars) {
    mbar_wait(bars + B_EP, 0);
    unsigned e;
    asm volatile("ld.shared.u32 %0, [%1];" : "=r"(e) : "r"(bars + B_EPOCH) : "memory");
    return e;
}
__device__ __forceinline__ void sts64(uint32_t a, uint32_t x, uint32_t y) { asm volatile("st.shared.v2.b32 [%0], {%1,%2};" ::"r"(a), "r"(x), "r"(y) : "memory"); }
__device__ __forceinline__ uint32_t pk(float lo, float hi) { uint32_t r; asm("cvt.rn.bf16x2.f32 %0, %1, %2;" : "=r"(r) : "f"(hi), "f"(lo)); return r; }
__device__ __forceinline__ float bf2f(unsigned short v) { return __uint_as_float((uint32_t)v << 16); }

__device__ __forceinline__ uint64_t mkdesc(uint32_t addr, uint32_t lbo, uint32_t sbo, uint32_t swz) {
    return (uint64_t)((addr & 0x3FFFF) >> 4) | ((uint64_t)(lbo >> 4) << 16) | ((uint64_t)(sbo >> 4) << 32) | ((uint64_t)swz << 62);
}
__device__ __forceinline__ uint64_t opaque(uint64_t v) { asm volatile("" : "+l"(v)); return v; }
__device__ __forceinline__ void wg_fence() { asm volatile("wgmma.fence.sync.aligned;" ::: "memory"); }
__device__ __forceinline__ void wg_commit() { asm volatile("wgmma.commit_group.sync.aligned;" ::: "memory"); }
template <int N> __device__ __forceinline__ void wg_wait() { asm volatile("wgmma.wait_group.sync.aligned %0;" ::"n"(N) : "memory"); }
template <int N> __device__ __forceinline__ void pin(float (&d)[N]) {
#pragma unroll
    for (int i = 0; i < N; i++) asm volatile("" : "+f"(d[i])::"memory");
}
template <int N> __device__ __forceinline__ void pinu(uint32_t (&d)[N]) {
#pragma unroll
    for (int i = 0; i < N; i++) asm volatile("" : "+r"(d[i])::"memory");
}

#define R8(d, o) "+f"(d[o]), "+f"(d[o + 1]), "+f"(d[o + 2]), "+f"(d[o + 3]), "+f"(d[o + 4]), "+f"(d[o + 5]), "+f"(d[o + 6]), "+f"(d[o + 7])
#define L8 "%0,%1,%2,%3,%4,%5,%6,%7"
#define L32 L8 ",%8,%9,%10,%11,%12,%13,%14,%15,%16,%17,%18,%19,%20,%21,%22,%23,%24,%25,%26,%27,%28,%29,%30,%31"
#define L56 L32 ",%32,%33,%34,%35,%36,%37,%38,%39,%40,%41,%42,%43,%44,%45,%46,%47,%48,%49,%50,%51,%52,%53,%54,%55"
#define L64 L56 ",%56,%57,%58,%59,%60,%61,%62,%63"

template <int O, int TA, int TB, int N> __device__ __forceinline__ void mma128_ss(float (&d)[N], uint64_t da, uint64_t db, int sc) {
    asm volatile("{.reg .pred p; setp.ne.b32 p, %66, 0;\n"
                 "wgmma.mma_async.sync.aligned.m64n128k16.f32.bf16.bf16 {" L64 "}, %64, %65, p, 1, 1, %67, %68;}"
                 : R8(d, O), R8(d, O + 8), R8(d, O + 16), R8(d, O + 24), R8(d, O + 32), R8(d, O + 40), R8(d, O + 48), R8(d, O + 56)
                 : "l"(da), "l"(db), "r"(sc), "n"(TA), "n"(TB));
}
template <int O, int TB> __device__ __forceinline__ void mma128_rs(float (&d)[128], uint32_t a0, uint32_t a1, uint32_t a2, uint32_t a3, uint64_t db, int sc) {
    asm volatile("{.reg .pred p; setp.ne.b32 p, %69, 0;\n"
                 "wgmma.mma_async.sync.aligned.m64n128k16.f32.bf16.bf16 {" L64 "}, {%64,%65,%66,%67}, %68, p, 1, 1, %70;}"
                 : R8(d, O), R8(d, O + 8), R8(d, O + 16), R8(d, O + 24), R8(d, O + 32), R8(d, O + 40), R8(d, O + 48), R8(d, O + 56)
                 : "r"(a0), "r"(a1), "r"(a2), "r"(a3), "l"(db), "r"(sc), "n"(TB));
}
template <int TB> __device__ __forceinline__ void mma64_rs(float (&d)[32], uint32_t a0, uint32_t a1, uint32_t a2, uint32_t a3, uint64_t db, int sc) {
    asm volatile("{.reg .pred p; setp.ne.b32 p, %37, 0;\n"
                 "wgmma.mma_async.sync.aligned.m64n64k16.f32.bf16.bf16 {" L32 "}, {%32,%33,%34,%35}, %36, p, 1, 1, %38;}"
                 : R8(d, 0), R8(d, 8), R8(d, 16), R8(d, 24)
                 : "r"(a0), "r"(a1), "r"(a2), "r"(a3), "l"(db), "r"(sc), "n"(TB));
}
__device__ __forceinline__ void mma112_ss(float (&d)[64], uint64_t da, uint64_t db, int sc) {
    asm volatile("{.reg .pred p; setp.ne.b32 p, %58, 0;\n"
                 "wgmma.mma_async.sync.aligned.m64n112k16.f32.bf16.bf16 {" L56 "}, %56, %57, p, 1, 1, 0, 1;}"
                 : R8(d, 8), R8(d, 16), R8(d, 24), R8(d, 32), R8(d, 40), R8(d, 48), R8(d, 56)
                 : "l"(da), "l"(db), "r"(sc));
}
__device__ __forceinline__ void mma16_rs(float (&d)[64], uint32_t a0, uint32_t a1, uint32_t a2, uint32_t a3, uint64_t db, int sc) {
    asm volatile("{.reg .pred p; setp.ne.b32 p, %13, 0;\n"
                 "wgmma.mma_async.sync.aligned.m64n16k16.f32.bf16.bf16 {" L8 "}, {%8,%9,%10,%11}, %12, p, 1, 1, 1;}"
                 : R8(d, 0)
                 : "r"(a0), "r"(a1), "r"(a2), "r"(a3), "l"(db), "r"(sc));
}

__device__ __forceinline__ cf cmul(cf a, cf b) { return {fmaf(a.x, b.x, -a.y * b.y), fmaf(a.x, b.y, a.y * b.x)}; }
__device__ __forceinline__ cf cmulc(cf a, cf b) { return {fmaf(a.x, b.x, a.y * b.y), fmaf(a.y, b.x, -a.x * b.y)}; }
__device__ __forceinline__ cf cfma(cf a, cf b, cf c) { return {fmaf(a.x, b.x, fmaf(-a.y, b.y, c.x)), fmaf(a.x, b.y, fmaf(a.y, b.x, c.y))}; }
__device__ __forceinline__ cf csq(cf a) { return {fmaf(a.x, a.x, -a.y * a.y), (a.x * a.y) * 2.f}; }
__device__ __forceinline__ cf csel(int c, cf a, cf b) {
    cf r;
    asm("{.reg .pred p; setp.ne.s32 p, %2, 0; selp.f32 %0, %3, %5, p; selp.f32 %1, %4, %6, p;}" : "=f"(r.x), "=f"(r.y) : "r"(c), "f"(a.x), "f"(a.y), "f"(b.x), "f"(b.y));
    return r;
}
__device__ __forceinline__ cf cadd(cf a, cf b) { return {a.x + b.x, a.y + b.y}; }
__device__ __forceinline__ cf csub(cf a, cf b) { return {a.x - b.x, a.y - b.y}; }
__device__ __forceinline__ cf twice_minus(cf a, cf s) { return {fmaf(2.f, a.x, -s.x), fmaf(2.f, a.y, -s.y)}; }
__device__ __forceinline__ cf twid(int m, int M) {
    int r = ((m + M / 2) & (M - 1)) - M / 2;
    float s, c;
    __sincosf((float)r * (-6.283185307179586f / (float)M), &s, &c);
    return {c, s};
}
struct c2 { cf a, b; };
#define YP1 3
#define YP2 0
#define YP3 3
template <int Y> __device__ __forceinline__ void fin(c2& u) { if (Y & 1) asm volatile("pmevent 1;" : "+f"(u.a.x), "+f"(u.a.y), "+f"(u.b.x), "+f"(u.b.y)); }
template <int Y> __device__ __forceinline__ void fin(c2& u, c2& v) {
    if (Y & 2) asm volatile("pmevent 1;" : "+f"(u.a.x), "+f"(u.a.y), "+f"(u.b.x), "+f"(u.b.y), "+f"(v.a.x), "+f"(v.a.y), "+f"(v.b.x), "+f"(v.b.y));
}
__device__ __forceinline__ c2 mul2(c2 u, cf t) { return {cmul(u.a, t), cmul(u.b, t)}; }
__device__ __forceinline__ c2 mul2(c2 u, c2 t) { return {cmul(u.a, t.a), cmul(u.b, t.b)}; }
__device__ __forceinline__ c2 fma2(c2 u, cf t, c2 c) { return {cfma(u.a, t, c.a), cfma(u.b, t, c.b)}; }
__device__ __forceinline__ c2 fma2(c2 u, c2 t, c2 c) { return {cfma(u.a, t.a, c.a), cfma(u.b, t.b, c.b)}; }
__device__ __forceinline__ c2 twm2(c2 u, c2 s) { return {twice_minus(u.a, s.a), twice_minus(u.b, s.b)}; }
template <int Y> __device__ __forceinline__ void bfly(c2& u, c2& v) { const c2 t = u; u = {cadd(t.a, v.a), cadd(t.b, v.b)}; v = {csub(t.a, v.a), csub(t.b, v.b)}; fin<Y>(u, v); }
template <int Y> __device__ __forceinline__ void bfly_mi(c2& u, c2& v) {
    const c2 t = u, z = v;
    u = {{t.a.x + z.a.y, t.a.y - z.a.x}, {t.b.x + z.b.y, t.b.y - z.b.x}};
    v = {{t.a.x - z.a.y, t.a.y + z.a.x}, {t.b.x - z.b.y, t.b.y + z.b.x}};
    fin<Y>(u, v);
}
template <int Y> __device__ __forceinline__ void bfly_s(c2& u, c2& v) {
    const float s = 0.70710678118654752f;
    const c2 t = u, z = v;
    u = {{fmaf(s, z.a.x, t.a.x), fmaf(s, z.a.y, t.a.y)}, {fmaf(s, z.b.x, t.b.x), fmaf(s, z.b.y, t.b.y)}};
    v = {{fmaf(-s, z.a.x, t.a.x), fmaf(-s, z.a.y, t.a.y)}, {fmaf(-s, z.b.x, t.b.x), fmaf(-s, z.b.y, t.b.y)}};
    fin<Y>(u, v);
}
template <int Y, class T> __device__ __forceinline__ void bfly_tw(c2& u0, c2& v0, T t0, c2& u1, c2& v1, T t1) {
    v0 = fma2(v0, t0, u0); fin<Y>(v0);
    v1 = fma2(v1, t1, u1); fin<Y>(v1);
    const c2 a = twm2(u0, v0), b = twm2(u1, v1);
    u0 = v0; u1 = v1; v0 = a; v1 = b;
    fin<Y>(v0, v1);
}
template <bool TW, int Y> __device__ __forceinline__ void dft8(c2 (&v)[8], const cf (&tw)[8]) {
    if (TW) {
#pragma unroll
        for (int n = 1; n < 4; n++) { v[n] = mul2(v[n], tw[n]); fin<Y>(v[n]); }
        bfly_tw<Y>(v[0], v[4], tw[4], v[2], v[6], tw[6]);
        bfly_tw<Y>(v[1], v[5], tw[5], v[3], v[7], tw[7]);
    } else {
#pragma unroll
        for (int n = 0; n < 4; n++) bfly<Y>(v[n], v[n + 4]);
    }
    bfly<Y>(v[0], v[2]); bfly_mi<Y>(v[4], v[6]);
    bfly<Y>(v[1], v[3]); bfly_mi<Y>(v[5], v[7]);
    v[5] = {{v[5].a.x + v[5].a.y, v[5].a.y - v[5].a.x}, {v[5].b.x + v[5].b.y, v[5].b.y - v[5].b.x}};
    v[7] = {{v[7].a.y - v[7].a.x, -v[7].a.x - v[7].a.y}, {v[7].b.y - v[7].b.x, -v[7].b.x - v[7].b.y}};
    fin<Y>(v[5], v[7]);
    bfly<Y>(v[0], v[1]); bfly_s<Y>(v[4], v[5]); bfly_mi<Y>(v[2], v[3]); bfly_s<Y>(v[6], v[7]);
    const c2 t1 = v[1], t3 = v[3];
    v[1] = v[4]; v[4] = t1; v[3] = v[6]; v[6] = t3;
}

__device__ __forceinline__ void gather(uint64_t (&fv)[4], const uint8_t* a, int n) {
    asm volatile("{.reg .pred p0, p1, p2, p3;\n"
                 "setp.ge.s32 p0, %5, 0; setp.ge.s32 p1, %5, 4; setp.ge.s32 p2, %5, 8; setp.ge.s32 p3, %5, 12;\n"
                 "@p0 ld.relaxed.gpu.global.b64 %0, [%4]; @p1 ld.relaxed.gpu.global.b64 %1, [%4+-32768];\n"
                 "@p2 ld.relaxed.gpu.global.b64 %2, [%4+-65536]; @p3 ld.relaxed.gpu.global.b64 %3, [%4+-98304];}"
                 : "+l"(fv[0]), "+l"(fv[1]), "+l"(fv[2]), "+l"(fv[3]) : "l"(a), "r"(n) : "memory");
}
__device__ __forceinline__ cf as_cf(uint64_t v) { cf r; asm("mov.b64 {%0,%1}, %2;" : "=f"(r.x), "=f"(r.y) : "l"(v)); return r; }
template <int H> __device__ __forceinline__ void prescale(float (&u)[64], const float (&d)[128], cf gam) {
#pragma unroll
    for (int i = 0; i < 32; i += 2) {
        const int r = 2 * i + 2 * H;
        c2 v = mul2(c2{{d[r], -d[64 + r]}, {d[r + 1], -d[65 + r]}}, gam);
        if (YS & 2) asm volatile("pmevent 1;" : "+f"(v.a.x), "+f"(v.a.y), "+f"(v.b.x), "+f"(v.b.y));
        u[i] = v.a.x; u[32 + i] = v.a.y; u[i + 1] = v.b.x; u[33 + i] = v.b.y;
    }
}
__device__ __forceinline__ void scan2(const float (&u)[64], cf lam, cf st, const uint8_t* hptr, uint32_t hm, uint32_t hb, uint32_t& keep) {
    uint32_t hp[32];
#pragma unroll
    for (int jj = 0; jj < 4; jj++) {
        cf v[8];
#pragma unroll
        for (int i = 0; i < 8; i++) v[i] = st = cfma(lam, st, {u[8 * jj + i], u[32 + 8 * jj + i]});
        const int o = 8 * jj;
        hp[o] = pk(v[0].x, v[2].x); hp[o + 1] = pk(v[4].x, v[6].x); hp[o + 2] = pk(v[1].x, v[3].x); hp[o + 3] = pk(v[5].x, v[7].x);
        hp[o + 4] = pk(v[0].y, v[2].y); hp[o + 5] = pk(v[4].y, v[6].y); hp[o + 6] = pk(v[1].y, v[3].y); hp[o + 7] = pk(v[5].y, v[7].y);
        hp[o + jj] = (hp[o + jj] & hm) | hb;
        hp[o + 4 + jj] = (hp[o + 4 + jj] & hm) | hb;
        stg128(hptr + (jj >> 1) * 8192 + (jj & 1) * 512, hp[o], hp[o + 1], hp[o + 2], hp[o + 3]);
        stg128(hptr + 16384 + (jj >> 1) * 8192 + (jj & 1) * 512, hp[o + 4], hp[o + 5], hp[o + 6], hp[o + 7]);
        YIELD_S3();
        if (jj > 0) {
#pragma unroll
            for (int i = o - 8; i < o; i += 2) asm volatile("lop3.b32 %0, %0, %1, %2, 0x80;" : "+r"(keep) : "r"(hp[i]), "r"(hp[i + 1]));
        }
    }
}

__device__ __forceinline__ int pos_of(int n) { return (n & 24) + 4 * (n & 1) + ((n >> 1) & 3); }
__device__ __forceinline__ int unit_of(int role, int u, int& slot) {
    const int g = role & 7, w = (role >> 3) & 3, b = role >> 5;
    slot = role >= 128 ? g : (g ? 16 * g + w + 4 * b : 4 * w + b);
    return role >= 128 ? 32 * max(2 * g + u, 1) : (g ? g + 16 * w : ((w & 1) << 4) + ((w & 2) << 2)) + 64 * b + 256 * u;
}
template <int STRIDE> __device__ __forceinline__ bool tags_ok(uint32_t a, uint32_t ep) {
    uint32_t v[4], ok;
#pragma unroll
    for (int i = 0; i < 4; i++) {
        if (STRIDE || !i) asm volatile("ld.shared.u32 %0, [%1];" : "=r"(v[i]) : "r"(a + i * STRIDE) : "memory");
        else v[i] = v[0];
    }
    asm volatile("{.reg .pred p; .reg .b32 a, b; lop3.b32 a, %1, %2, %5, 0x7e; lop3.b32 b, %3, %4, %5, 0x7e; lop3.b32 a, a, b, 1, 0xa8;\n"
                 "setp.eq.u32 p, a, 0; vote.sync.all.pred p, p, -1; selp.u32 %0, 1, 0, p;}" : "=r"(ok) : "r"(v[0]), "r"(v[1]), "r"(v[2]), "r"(v[3]), "r"(ep));
    return ok;
}
__device__ __forceinline__ void load_w_rows(uint32_t dst, const CUtensorMap* mr, const CUtensorMap* mi, int kap, uint32_t bar) {
    mbar_expect_tx(bar, 16 * WPITCH);
#pragma unroll 1
    for (int i = 0; i < 2; i++, dst += 8 * WPITCH, kap = (512 - kap) & 511) {
        tma2d(dst, mr, (kap * 1026 >> 4) * 2, 0, bar);
        tma2d(dst + 4 * WPITCH, mi, (kap * 1026 >> 4) * 2, 0, bar);
    }
}
__device__ __forceinline__ void prefetch_w_rows(const CUtensorMap* mr, const CUtensorMap* mi, int kap) {
#pragma unroll 1
    for (int i = 0; i < 2; i++, kap = (512 - kap) & 511) {
        asm volatile("cp.async.bulk.prefetch.tensor.2d.L2.global [%0, {%1,%2}];" ::"l"(mr), "r"((kap * 1026 >> 4) * 2), "r"(0) : "memory");
        asm volatile("cp.async.bulk.prefetch.tensor.2d.L2.global [%0, {%1,%2}];" ::"l"(mi), "r"((kap * 1026 >> 4) * 2), "r"(0) : "memory");
    }
}
template <int K0, int K1> __device__ __forceinline__ void store_v(const uint32_t (&vo)[32], const uint8_t* vp, bool p) {
    if (p) {
#pragma unroll
        for (int k = K0; k < K1; k++)
            asm volatile("st.global.v2.b32 [%0], {%1,%2};" ::"l"(vp + (k >> 2) * (1 << 20) + ((k >> 1) & 1) * 8192 + (k & 1) * (4 * 32768)), "r"(vo[2 * k]), "r"(vo[2 * k + 1]) : "memory");
    }
}
__device__ __forceinline__ void hint_v(unsigned* cnt, int on) { asm volatile("{.reg .pred p; setp.ne.and.u32 p, %1, 0, p0; @p red.relaxed.gpu.global.add.u32 [%0], 1;}" ::"l"(cnt), "r"(on) : "memory"); }
#define SB0 1024
__device__ __forceinline__ uint64_t ring_desc(uint32_t sb, uint32_t off, uint32_t lbo, uint32_t swz) {
    uint64_t d;
    asm volatile("{.reg .b32 z; shr.u32 z, %1, 28; mov.b64 %0, {z, z}; add.u64 %0, %0, %2;}" : "=l"(d) : "r"(sb), "l"(mkdesc(SB0 + off, lbo, 1024, swz)));
    return d;
}
struct Ring {
    uint32_t full, rel;
    uint32_t n;
    bool sig;
};
__device__ __forceinline__ void ring_release(const Ring& r, uint32_t o) {
    if (r.sig) asm volatile("mbarrier.arrive.shared::cluster.b64 _, [%0];" ::"r"(r.rel + o) : "memory");
}
__device__ __forceinline__ void peek(uint32_t a, uint32_t ph) { asm volatile("mbarrier.test_wait.parity.shared::cta.b64 pk, [%0], %1;" ::"r"(a), "r"(ph) : "memory"); }
__device__ __forceinline__ void peek_wait(uint32_t a, uint32_t ph, uint32_t& n) {
    asm volatile("{@pk bra DONE;\n"
                 "LOOP: mbarrier.try_wait.parity.shared::cta.b64 pk, [%1], %2; add.u32 %0, %0, 1; setp.gt.or.u32 pk, %0, %3, pk; @!pk bra LOOP;\n"
                 "DONE: }" : "+r"(n) : "r"(a), "r"(ph), "n"(SPIN_LIMIT) : "memory");
}
#define SL(k) ((k) % NST)
#define PH(k) (((k) / NST) & 1)
#define HANDPOS 5
#define H64 "%64,%65,%66,%67,%68,%69,%70,%71,%72,%73,%74,%75,%76,%77,%78,%79,%80,%81,%82,%83,%84,%85,%86,%87,%88,%89,%90,%91,%92,%93,%94,%95," \
            "%96,%97,%98,%99,%100,%101,%102,%103,%104,%105,%106,%107,%108,%109,%110,%111,%112,%113,%114,%115,%116,%117,%118,%119,%120,%121,%122,%123,%124,%125,%126,%127"
#define WG_MMA "wgmma.mma_async.sync.aligned.m64n128k16.f32.bf16.bf16 "
#define DESC_B(S, j) "mov.b64 {t, hb}, %130; mov.b64 db, {%137 + 2048 * " #S " + 2 * " #j ", hb};\n"
#define MMA_LO(S, j, p) "add.u64 da, %129, 2048 * " #S " + %136 * " #j ";" DESC_B(S, j) WG_MMA "{" L64 "}, da, db, " #p ", 1, 1, %138, 0;\n"
#define MMA_HI(S, j, p) "add.u64 da, %129, 2048 * " #S " + 512 + %136 * " #j ";\n" WG_MMA "{" H64 "}, da, db, " #p ", 1, 1, %138, 0;\n"
#define X3(X)
#define X4(X)
#define X5(X) X
#define STEP(S, P, N, ph, pa, pr, X, Y) \
    "wgmma.fence.sync.aligned;\n" MMA_LO(S, 0, pa) MMA_HI(S, 0, pa) \
    "wgmma.commit_group.sync.aligned; wgmma.wait_group.sync.aligned 1; @" #pr " mbarrier.arrive.shared::cluster.b64 _, [%132 + 8 * " #P "];\n" MMA_LO(S, 1, 1) \
    "mbarrier.test_wait.parity.shared::cta.b64 pk, [%131 + 8 * " #N "], " #ph ";\n" X3(X) MMA_HI(S, 1, 1) X4(X) MMA_LO(S, 2, 1) X5(X) MMA_HI(S, 2, 1) MMA_LO(S, 3, 1) MMA_HI(S, 3, 1) \
    "wgmma.commit_group.sync.aligned;\n" P4A Y "@pk bra GO" #S ";\n" \
    "WAIT" #S ": mbarrier.try_wait.parity.shared::cta.b64 pk, [%131 + 8 * " #N "], " #ph "; add.u32 %128, %128, 1; setp.gt.or.u32 pk, %128, %139, pk; @!pk bra WAIT" #S ";\n" \
    "GO" #S ":\n" P4B
#define P4A
#define P4B
#define P4I
#define P4O
#define STEP_ARGS(TA) \
    : R8(d, 0), R8(d, 8), R8(d, 16), R8(d, 24), R8(d, 32), R8(d, 40), R8(d, 48), R8(d, 56), \
      R8(d, 64), R8(d, 72), R8(d, 80), R8(d, 88), R8(d, 96), R8(d, 104), R8(d, 112), R8(d, 120), "+r"(r.n) \
    : "l"(ha), "l"(hb), "r"(r.full), "r"(r.rel), "r"((uint32_t)r.sig), "r"(wg), \
      "n"(SB0 / 16 + (TA ? 32 << 16 : 1 << 16)), "n"(TA ? 128 : 2), "n"(SB0 / 16 + 1024 + (1 << 16)), "n"(TA), "n"(SPIN_LIMIT) P4O \
    : "memory"
#define STEP_REGS "{.reg .b32 k, t, ph, hb; .reg .b64 da, db; .reg .pred ps, pl, pa, pr;\n" P4I "setp.ne.u32 ps, %133, 0;\n"
#define FIRST_WAIT "FIRST: mbarrier.try_wait.parity.shared::cta.b64 pk, [t], ph; @pk bra START; add.u32 %128, %128, 1; setp.le.u32 pk, %128, %139; @pk bra FIRST; START:\n"
__device__ __forceinline__ void gemm1(float (&d)[128], Ring& r, uint64_t ha, uint64_t hb, int wg) {
    asm volatile(STEP_REGS "mul.lo.u32 k, %134, 15; mov.b32 ph, %134; setp.ne.u32 pl, k, 0; mad.lo.u32 t, %134, 8, %131;\n"
                 "pmevent 1; @pl bar.sync 1, 256;\n" FIRST_WAIT "@pl bra ONE;\n"
                 "LOOP: setp.ne.u32 pa, k, 0; and.pred pr, pa, ps; setp.eq.u32 pl, k, 15;\n"
                 STEP(0, 4, 1, ph, pa, pr, "@pl bar.arrive 1, 256;\n", "@pl bra END;\n")
                 "ONE: setp.ne.u32 pa, k, 15; and.pred pr, pa, ps; setp.eq.u32 pl, k, 30;\n"
                 STEP(1, 0, 2, ph, pa, pr, "@pl bar.arrive 2, 256;\n", "@pl bra END;\n")
                 STEP(2, 1, 3, ph, 1, ps, "", "") STEP(3, 2, 4, ph, 1, ps, "", "") "xor.b32 ph, ph, 1; add.u32 k, k, 5;\n" STEP(4, 3, 0, ph, 1, ps, "", "")
                 "bra LOOP;\n"
                 "END:\n" P4B "}" STEP_ARGS(0));
}
__device__ __forceinline__ void gemm2(float (&d)[128], Ring& r, uint64_t ha, uint64_t hb, int wg) {
    asm volatile(STEP_REGS "mov.b32 k, 0; mov.b32 ph, 0; add.u32 t, %131, 16;\n"
                 "pmevent 1; bar.sync 2, 256;\n" FIRST_WAIT
                 "LOOP: setp.ne.u32 pa, k, 0; and.pred pr, pa, ps; setp.eq.u32 pl, k, 5;\n"
                 STEP(2, 1, 3, ph, pa, pr, "", "") STEP(3, 2, 4, ph, 1, ps, "", "") "xor.b32 ph, ph, 1; add.u32 k, k, 1;\n" STEP(4, 3, 0, ph, 1, ps, "", "")
                 "@pl bra END;\n" STEP(0, 4, 1, ph, 1, ps, "", "") STEP(1, 0, 2, ph, 1, ps, "", "")
                 "bra LOOP;\n"
                 "END: }" STEP_ARGS(1));
}
template <int O, int K, int J> __device__ __forceinline__ void mma_h(float (&y)[128], uint64_t a, uint64_t b) { mma128_ss<O, 1, 0>(y, a + SL(K) * 2048 + O * 8 + 128 * J, b + SL(K) * 2048 + 2 * J, 1); }
template <int O, int K> __device__ __forceinline__ void half_step(float (&y)[128], uint64_t a, uint64_t b) { mma_h<O, K, 0>(y, a, b); mma_h<O, K, 1>(y, a, b); mma_h<O, K, 2>(y, a, b); mma_h<O, K, 3>(y, a, b); }
template <int R, int U> __device__ __forceinline__ void out_piece(float (&y)[128], const uint32_t (&dd)[16], uint32_t x0, uint32_t x1, float* op) {
    const int i = 64 * (R >> 1) + 8 * U + 2 * (R & 1);
    asm("mul.rn.bf16x2 %0, %0, %1;" : "+r"(x0) : "r"(dd[2 * U]));
    asm("mul.rn.bf16x2 %0, %0, %1;" : "+r"(x1) : "r"(dd[2 * U + 1]));
    asm volatile("st.global.v4.f32 [%0], {%1,%2,%3,%4};" ::"l"(op + (32 * (R & 1) + 16 * (R >> 1)) * 2048 + 16 * U),
                 "f"(y[i] + __uint_as_float(x0 << 16)), "f"(y[i + 1] + __uint_as_float(x0 & 0xffff0000u)),
                 "f"(y[i + 4] + __uint_as_float(x1 << 16)), "f"(y[i + 5] + __uint_as_float(x1 & 0xffff0000u)) : "memory");
}
template <int R, int U0> __device__ __forceinline__ void load_x4(uint32_t (&xx)[8], uint32_t xa) {
#pragma unroll
    for (int u = 0; u < 4; u++)
        asm volatile("ld.shared.v2.b32 {%0,%1}, [%2];" : "=r"(xx[2 * u]), "=r"(xx[2 * u + 1]) : "r"((xa ^ (u << 5)) + (3 - R) * 8192 + U0 * 1024) : "memory");
}
__device__ __forceinline__ Ring ring_at(uint32_t sb, int k) {
    Ring r;
    r.n = 0;
    r.full = sb + OFF_BAR + B_FULL;
    asm("mapa.shared::cluster.u32 %0, %1, %2;" : "=r"(r.rel) : "r"(sb + OFF_BAR + B_EMPTY), "r"((threadIdx.x >> 5) & 1));
    r.sig = __shfl_sync(~0u, threadIdx.x & 95, threadIdx.x) == 0;
    return r;
}

template <bool BY_SM> __global__ void __cluster_dims__(2, 1, 1) __launch_bounds__(512, 1)
fused_kernel(const __grid_constant__ CUtensorMap tmX, const __grid_constant__ CUtensorMap tmBre, const __grid_constant__ CUtensorMap tmBim,
             const __grid_constant__ CUtensorMap tmCre, const __grid_constant__ CUtensorMap tmCim, const __grid_constant__ CUtensorMap tmXd,
             const __grid_constant__ CUtensorMap tmUst, const __grid_constant__ CUtensorMap tmVst,
             const __grid_constant__ CUtensorMap tmWr, const __grid_constant__ CUtensorMap tmWi, const __grid_constant__ CUtensorMap tmXa,
             const Params p) {
    extern __shared__ __align__(1024) uint8_t smraw[];
    asm volatile(".reg .pred pk, p0;");
    const int tid = TIDMAP, rank = blockIdx.x & 1;
    const uint32_t wi = __shfl_sync(~0u, smem_u32(smraw) + (tid >> 5), 0), sb = wi & ~15u, bars = sb + OFF_BAR;
    const int wg = (wi >> 2) & 3, w = wi & 3, lane = tid & 31, g = lane >> 2, q = lane & 3;
    if (wg != 3) asm volatile("barrier.cluster.arrive.relaxed.aligned; barrier.cluster.wait.aligned;" ::: "memory");
    else asm volatile("prefetch.tensormap [%0];" ::"l"(w == 0 ? &tmX : w == 1 ? &tmBre : &tmBim) : "memory");
    int role;
    {
        uint32_t T = blockIdx.x;
        if (BY_SM) asm("mov.u32 %0, %%smid;" : "=r"(T));
        T >>= 1;
        const uint32_t a = ((T - 32) * 37) >> 8;
        asm("{.reg .pred p; setp.lt.u32 p, %1, 62; selp.u32 %0, 4, -58, p; add.u32 %0, %0, %1;\n"
            "setp.lt.u32 p, %1, 60; selp.u32 %0, %2, %0, p; setp.lt.u32 p, %1, 32; selp.u32 %0, %3, %0, p;}"
            : "=&r"(role) : "r"(T), "r"(8 * (T - 31 - 7 * a) + 4 + a), "r"(8 * (T & 7) + (T >> 3)));
        role = 2 * role + rank;
    }
    const bool spare = role >= 128;
    const int tc = ((role >> 3) & 14) + rank, cb = (role >> 1) & 7;
    const int fb = role >> 5, fcb = role & 31, fpos = pos_of(fcb);
    const int nu = role == 128 ? 1 : (fcb || !role ? 2 : 0);

    if (wg == 3) {
        if (elect_one()) {
            const uint32_t b = bars + w * 8;
            STAMP5(57);
            mbar_init(b, 1);
            if (w < XW && !spare) {
                mbar_expect_tx(b, 32768);
                tma5d(sb + w * 32768 + 16384, &tmX, w * 64, 0, 0, 0, tc, b);
                if (w == 0) { tma4d(sb, &tmBre, 0, 0, 0, cb * 4, b); tma4d(sb + 8192, &tmBim, 0, 0, 0, cb * 4, b); }
                STAMP5(58);
            }
#pragma unroll
            for (int o = 32; o < B_EPOCH; o += 32) mbar_init(b + o, o < B_EMPTY ? 1 : (o < B_STG ? 2 : (o < B_P3M ? 4 : 8)));
            asm volatile("fence.mbarrier_init.release.cluster;" ::: "memory");
        }
        __syncwarp();
        STAMP5(59);
        asm volatile("barrier.cluster.arrive.relaxed.aligned;" ::: "memory");
    }
    if (opaque32(wg) == 3) {
        asm volatile("setmaxnreg.dec.sync.aligned.u32 24;");
        asm volatile("barrier.cluster.wait.aligned;" ::: "memory");
        if (w == 0) {
            if (!spare && elect_one()) {
                STAMP(56);
#pragma unroll 1
                for (int k = 1; k < NST; k++) {
                    if (k >= XW) mbar_expect_tx(bars + B_FULL + k * 8, 32768);
                    tma4d_mc(sb + k * 32768 + rank * 8192, rank ? &tmBim : &tmBre, k * 64, 0, 0, cb * 4, bars + B_FULL + k * 8);
                    if (k >= XW) tma5d(sb + k * 32768 + 16384, &tmX, k * 64, 0, 0, 0, tc, bars + B_FULL + k * 8);
                }
#define RING_WAIT "mbarrier.try_wait.parity.shared::cta.b64 p, [fb + 256], ph; @p bra GO;\n" \
                  "WAIT: mbarrier.try_wait.parity.shared::cta.b64 p, [fb + 256], ph; add.u32 n, n, 1; setp.gt.or.u32 p, n, 32768, p; @!p bra WAIT;\nGO:\n"
#define RING_NEXT "pmevent 1; add.u32 o, o, 8; setp.eq.u32 p, o, 40; selp.u32 o, 0, o, p; @p xor.b32 ph, ph, 1; add.u32 fb, %1, o; shl.b32 t, o, 12; add.u32 da, %0, t;\n"
                asm volatile("{.reg .b32 o, k, kk, c2, da, db, fb, ph, n, t; .reg .pred p;\n"
                             "mov.b32 o, 0; mov.b32 k, 320; mov.b32 kk, 320; mov.b32 c2, 0; mov.b32 ph, 0; mov.b32 n, 0; mov.b32 fb, %1; mov.b32 da, %0; mov.b32 db, %2;\n"
                             "LOOP:\n" RING_WAIT
                             "cp.async.bulk.tensor.5d.shared::cluster.global.mbarrier::complete_tx::bytes [da], [%3, {kk,0,0,0,%5}], [fb];\n"
                             "cp.async.bulk.tensor.4d.shared::cluster.global.mbarrier::complete_tx::bytes.multicast::cluster [db], [%4, {kk,0,c2,%6}], [fb], %7;\n"
                             "mbarrier.arrive.expect_tx.shared::cta.b64 _, [fb], 32768;\n" RING_NEXT
                             "add.u32 db, %2, t; add.u32 k, k, 64; and.b32 kk, k, 1023; shr.u32 c2, k, 9; and.b32 c2, c2, 2; setp.ne.u32 p, k, 2048; @p bra LOOP;}"
                             ::"r"(sb + 16384), "r"(bars + B_FULL), "r"(sb + rank * 8192), "l"(&tmX), "l"(rank ? &tmBim : &tmBre), "r"(tc), "r"(cb * 4), "h"((uint16_t)3) : "memory");
                asm volatile("{.reg .b32 o, k, kk, da, db, fb, hb, ph, n, t; .reg .b64 m, src; .reg .pred p;\n"
                             "mov.b32 o, 16; mov.b32 k, 0; mov.b32 kk, 0; mov.b32 ph, 1; mov.b32 n, 0; add.u32 fb, %1, 16; add.u32 hb, %1, 72; add.u32 da, %0, 65536; add.u32 db, %2, 65536;\n"
                             "mov.b64 m, %3; mov.b64 src, %5;\n"
                             "GROUP: add.u32 t, %8, k;\n"
                             "OWN: mbarrier.try_wait.parity.shared::cta.b64 p, [t], 0; add.u32 n, n, 1; setp.gt.or.u32 p, n, 32768, p; @!p bra OWN;\n"
                             "LOOP:\n" RING_WAIT
                             "cp.async.bulk.shared::cluster.global.mbarrier::complete_tx::bytes [da], [src], 16384, [hb];\n"
                             "cp.async.bulk.tensor.5d.shared::cluster.global.mbarrier::complete_tx::bytes.multicast::cluster [db], [m, {kk,0,0,0,%6}], [fb], %7;\n"
                             "mbarrier.expect_tx.shared::cta.b64 [fb], 16384; mbarrier.arrive.expect_tx.shared::cta.b64 _, [hb], 16384;\n" RING_NEXT
                             "add.u32 db, %2, t; add.u64 src, src, 16384; sub.u64 m, %4, m; add.u32 k, k, 1; shl.b32 kk, k, 5; and.b32 kk, kk, 0x7c0;\n"
                             "and.b32 t, k, 1; mad.lo.u32 hb, t, 8, fb; add.u32 hb, hb, o; add.u32 hb, hb, 40;\n"
                             "and.b32 t, k, 7; setp.ne.u32 p, t, 0; @p bra LOOP; setp.ne.u32 p, k, 32; @p bra GROUP;}"
                             ::"r"(sb), "r"(bars + B_FULL), "r"(sb + 16384 + rank * 8192), "l"(&tmCre), "l"((uint64_t)&tmCre + (uint64_t)&tmCim),
                               "l"(g_H + (size_t)tc * 32 * 16384), "r"(cb * 8 + rank * 4), "h"((uint16_t)3), "r"(bars + B_HOWN) : "memory");
            }
        } else if (opaque32(w) == 1) {
            const unsigned ep = ld_rlx(g_epoch + role * 8) + 1;
            __syncwarp();
            if (elect_one()) {
                asm volatile("st.relaxed.gpu.global.u32 [%0], %1;" ::"l"(g_epoch + role * 8), "r"(ep) : "memory");
                asm volatile("st.shared.u32 [%0], %1;" ::"r"(bars + B_EPOCH), "r"(ep) : "memory");
                mbar_arrive(bars + B_EP);
            }
            int slot;
            const int kap = unit_of(role, 0, slot), kap1 = unit_of(role, 1, slot);
            uint32_t lph = 0;
            if (!spare) mbar_wait(bars + B_STGU, 0);
            STAMP(21);
            const int c0 = fb * 2048 + fpos * 64;
            if (elect_one()) {
                if (!spare) {
#pragma unroll 1
                    for (int r = 4; r < 8; r++) bulk_st(g_X + r * (32 * 16384) + c0 * 2, sb + OFF_P + r * 4096, 128);
                    tma2d_st(&tmUst, c0, 0, sb + OFF_P);
                    bulk_commit();
                    tma2d_st(&tmUst, c0, 64, sb + OFF_P + 8192);
                    bulk_commit();
                    if (UHINT == 1) asm volatile("cp.async.bulk.wait_group.read 1;" ::: "memory");
                    if (UHINT < 2) red_hint(g_cnt);
                }
                mbar_expect_tx(bars + B_FG, 8192);
                bulk_ld(sb + OFF_F, (const uint8_t*)g_tab + TAB_FG, 8192, bars + B_FG);
            }
            STAMP(40);
#pragma unroll 1
            for (int e = 0; e < 4; e++) {
                if (e >= 2) {
                    if (e == nu) {
                        mbar_wait(bars + B_WFREE, 0);
                        if (elect_one()) load_w_rows(sb + OFF_WD, &tmWr, &tmWi, kap1, bars + B_WD);
                    }
                    if (e - 2 < nu) mbar_wait(bars + B_STG, e & 1);
                    STAMPO(23, e - 2);
                    if (e == nu && elect_one()) {
                        const int c = (role ? slot : 256) * 32;
                        tma2d_st(&tmVst, c, 0, sb + OFF_P);
                        bulk_commit();
                        tma2d_st(&tmVst, c + 4096, 0, sb + OFF_P + 8192);
                        bulk_commit();
                        if (role) { asm volatile("cp.async.bulk.wait_group.read %0;" ::"n"(V0T) : "memory"); red_hint(g_cnt + 64); } else bulk_wait_all();
                        if (spare) bulk_wait_read();
                    }
                    if (e == 3 && !spare && elect_one()) {
                        mbar_expect_tx(bars + B_FG, 8192);
                        bulk_ld(sb + OFF_F, (const uint8_t*)g_tab + TAB_G + fb * 8192, 8192, bars + B_FG);
                    }
                }
                const uint32_t tg = e < 2 ? lane * 128 + ((((lane >> 1) & 2) ^ (lane & 3)) << 4) + (lane >> 3) * 4 : lane * 64 + (lane & 8) * 4 + (lane & 2) * 8 + (lane & 4) * 2;
                if (spare) {
                    if (e == 1) {
                        wait_cnt(g_cnt, 128 * ep);
                        STAMP(42);
#pragma unroll 1
                        for (int n = 0; n < 4096; n++) {
                            if (elect_one()) {
                                mbar_expect_tx(bars + B_LD, 8 * 16384);
#pragma unroll 1
                                for (int r = 0; r < 8; r++) bulk_ld(sb + r * 16384, g_X + (size_t)r * (32 * 16384), 16384, bars + B_LD);
                            }
                            mbar_wait(bars + B_LD, n & 1);
                            bool ok = true;
#pragma unroll 1
                            for (int r = 0; r < 8; r++) ok &= tags_ok<4096>(sb + r * 16384 + tg, ep);
                            if (ok) break;
                        }
                        if (elect_one()) mbar_arrive(bars + B_RAW);
                    }
                } else {
                    const uint32_t dst = sb + OFF_P + (e & 1) * 16384;
                    wait_cnt(g_cnt + e * 32, 128 * ep);
                    STAMPO(41, e == 2 ? -12 : e);
#pragma unroll 1
                    for (int n = 0; n < 4096; n++) {
                        if (elect_one()) {
                            bulk_wait_read();
                            mbar_expect_tx(bars + B_LD, 16384);
                            bulk_ld(dst, g_X + (size_t)(e < 2 ? role + e * 128 : 254 + (fb * 32 + fpos) * 2 + e) * 16384, 16384, bars + B_LD);
                            if (U1POS <= 0 && e + n == 0) {
                                if (U1POS < 0 && nu) load_w_rows(sb + OFF_WD, &tmWr, &tmWi, kap, bars + B_WD);
                                tma2d_st(&tmUst, c0, 128, dst + 16384); tma2d_st(&tmUst, c0, 192, dst + 24576); bulk_commit();
                                if (U1POS == -2) { bulk_wait_read(); red_hint(g_cnt + 32); }
                            }
                        }
                        mbar_wait(bars + B_LD, lph);
                        if (!e) STAMP3(49);
                        lph ^= 1;
                        if (tags_ok<4096>(dst + tg, ep) & tags_ok<4096>(dst + tg + (e & 2) * 1024, ep) & tags_ok<0>(dst + (e == 3 ? (lane & 1) * 8192 + 32 : 0), ep)) break;
                    }
                    if (elect_one()) mbar_arrive(bars + B_IN + e * 8);
                }
                if (e < 2 && elect_one()) {
                    if (e) prefetch_w_rows(&tmWr, &tmWi, kap1);
                    else {
                        if (U1POS < 0 ? spare : nu) load_w_rows(sb + OFF_WD, &tmWr, &tmWi, kap, bars + B_WD);
                        if (!spare && U1POS != -2) {
                            if (U1POS > 0) { tma2d_st(&tmUst, c0, 128, sb + OFF_P + 16384); bulk_commit(); tma2d_st(&tmUst, c0, 192, sb + OFF_P + 24576); bulk_commit(); }
                            if (U1POS == 2) asm volatile("cp.async.bulk.wait_group.read 1;" ::: "memory"); else bulk_wait_read();
                            red_hint(g_cnt + 32);
                        }
                    }
                }
            }
            if (!spare) {
                mbar_wait(bars + B_HOWN + 8, 0);
#pragma unroll 1
                for (int r = 0; r < 4; r++) {
                    if (r == 3) mbar_wait(bars + B_P3M, 0);
                    if (elect_one()) {
                        if (r == 0) { mbar_expect_tx(bars + B_XD, 24576 + 256); mbar_expect_tx(bars + B_XD + 8, 8192); bulk_ld(sb + OFF_LAM, p.dsk + cb * 128, 256, bars + B_XD); }
                        tma4d(sb + OFF_F + (3 - r) * 8192, &tmXd, 0, tc * 128 + 32 * (r & 1) + 16 * (r >> 1), 0, cb * 2, bars + B_XD + (r == 3) * 8);
                    }
                    __nanosleep(PACE_X);
                }
            }
        } else {
            if (w == 2) {
                {
                    const int u = lane >> 4;
                    int slot;
                    const int r0 = unit_of(role, u, slot) + 512 * ((lane >> 1) & 3), r1 = (2048 - r0) & 2047, mir = (lane >> 3) & 1;
                    const unsigned short* wp = (const unsigned short*)((lane & 1) ? p.wi : p.wr);
                    const float a = bf2f(wp[r0 * 513 + mir * 512]), b = bf2f(wp[r1 * 513 + mir * 512]);
                    asm volatile("st.shared.f32 [%0], %1;" ::"r"(sb + OFF_WSP + u * 64 + (lane & 15) * 4), "f"(0.5f * ((lane & 1) ? (mir ? b - a : a - b) : a + b)) : "memory");
                }
                warp_arrive(bars + B_WSP);
            } else if (!spare) {
                if (XA_T0) __nanosleep(XA_T0);
#pragma unroll 1
                for (int i = 0; i < 8; i++) {
                    if (i >= XA_N0) __nanosleep(XA_PACE);
                    if (elect_one()) {
                        const uint32_t xb = bars + (P1H && i < 4 ? B_RAW : B_XIN);
                        if (P1H ? !(i & 3) : !i) mbar_expect_tx(xb, P1H ? 16384 : 32768);
                        tma3d(sb + OFF_F + i * 4096, &tmXa, fcb * 32, 0, 4 * i + fb, xb);
                    }
                }
            }
            if (!spare) {
                if (w == 2 && nu) {
                    int slot;
                    const int kap = unit_of(role, 0, slot);
                    mbar_wait(bars + WPFB, 0);
                    if (elect_one()) prefetch_w_rows(&tmWr, &tmWi, kap);
                }
                const unsigned ep = get_epoch(bars);
#define CNT_RETRY
#define CNT_ARG
                asm volatile("{.reg .b32 o, k, hb, fb, ca, m, ph, rph, n, t, v0, v1, v2, v3; .reg .b64 src; .reg .pred p, pe;\n"
                             "elect.sync _|pe, 0xffffffff; mov.b32 o, %0; shr.u32 k, %0, 3; sub.u32 k, k, 2; mov.b32 m, 0x107c0; mov.b32 rph, 0; mov.b32 n, 0;\n"
                             "bra NEXT;\n"
                             "LOOP: mbarrier.try_wait.parity.shared::cta.b64 p, [hb], ph; @p bra GO;\n"
                             "WAIT: mbarrier.try_wait.parity.shared::cta.b64 p, [hb], ph; add.u32 n, n, 1; setp.gt.or.u32 p, n, 32768, p; @!p bra WAIT;\n"
                             "GO: ld.shared.u32 v0, [ca]; ld.shared.u32 v1, [ca + 128]; ld.shared.u32 v2, [ca + 256]; ld.shared.u32 v3, [ca + 384];\n"
                             "lop3.b32 v0, v0, v1, %4, 0x7e; lop3.b32 v2, v2, v3, %4, 0x7e; lop3.b32 v0, v0, v2, 1, 0xa8; setp.eq.u32 p, v0, 0; vote.sync.all.pred p, p, -1; @p bra OK;\n"
                             CNT_RETRY "add.u32 n, n, 16; setp.gt.u32 p, n, 32768; @p bra OK;\n"
                             "shl.b32 t, o, 12; add.u32 t, t, %5; mad.wide.u32 src, k, 16384, %6;\n"
                             "@pe mbarrier.arrive.expect_tx.shared::cta.b64 _, [%7], 16384; @pe cp.async.bulk.shared::cluster.global.mbarrier::complete_tx::bytes [t], [src], 16384, [%7];\n"
                             "AGAIN: mbarrier.try_wait.parity.shared::cta.b64 p, [%7], rph; add.u32 n, n, 1; setp.gt.or.u32 p, n, 32768, p; @!p bra AGAIN;\n"
                             "xor.b32 rph, rph, 1; bra GO;\n"
                             "OK: @pe mbarrier.arrive.shared::cta.b64 _, [fb]; pmevent 1;\n"
                             "add.u32 o, o, 16; setp.ge.u32 p, o, 40; @p sub.u32 o, o, 40; add.u32 k, k, 2;\n"
                             "NEXT: shr.u32 m, m, 1; and.b32 ph, m, 1; add.u32 fb, %1, o; mad.lo.u32 hb, o, 2, %2; mad.lo.u32 ca, o, 4096, %3; setp.lt.u32 p, k, 32; @p bra LOOP;}"
                             ::"r"(8 * w), "r"(bars + B_FULL), "r"(bars + B_HL - 16 + w * 8), "r"(sb + (q >> 1) * 8192 + (q & 1) * 512 + g * 1040 + q * 4), "r"(ep),
                               "r"(sb), "l"(g_H + (size_t)tc * 32 * 16384), "r"(bars + B_HR - 16 + w * 8) CNT_ARG : "memory");
                if (w == 3) warp_arrive(bars + B_DONE);
            }
        }
    } else {
        STAMP(55);
        asm volatile("setmaxnreg.inc.sync.aligned.u32 152;");
        STAMP5(60);
        const int t7 = tid & 127, hf = wg - 1;
        const int mi = lane >> 3, gl = lane & 7;
        if (spare && wg != 2) {
            if (tid < 64) { const uint4 v = __ldg((const uint4*)((const uint8_t*)g_tab + TAB_PC) + tid); sts128(sb + OFF_LAM + tid * 16, v.x, v.y, v.z, v.w); }
            bar_sync(1, 256);
            mbar_wait(bars + B_RAW, 0);
            STAMP(0);
#pragma unroll 1
            for (int u = 0; u < nu; u++) {
                int slot;
                const int t = unit_of(role, u, slot) >> 5;
                const uint32_t off = (tid >> 2) * 128 + q * 16;
                float zr[16], zi[16];
#pragma unroll
                for (int k = 0; k < 16; k++) zr[k] = zi[k] = 0.f;
#pragma unroll 1
                for (int r = (t & 1) ? 0 : t >> 1; r < 8 - ((t & 1) ? 0 : (t >> 1) - 1); r += (t & 1) ? 1 : 8 - t) {
                    float4 c;
                    float a[8], b[8];
                    lds128f(sb + OFF_LAM + t * 128 + r * 16, c.x, c.y, c.z, c.w);
                    lds128f(sb + r * 16384 + off, a[0], a[1], a[2], a[3]);
                    lds128f(sb + r * 16384 + off + 64, b[0], b[1], b[2], b[3]);
                    lds128f(sb + r * 16384 + off + 8192, a[4], a[5], a[6], a[7]);
                    lds128f(sb + r * 16384 + off + 8192 + 64, b[4], b[5], b[6], b[7]);
#pragma unroll
                    for (int k = 0; k < 16; k++) {
                        const uint32_t ua = __float_as_uint(a[k >> 1]), ub = __float_as_uint(b[k >> 1]);
                        const float x = __uint_as_float((k & 1) ? ua & 0xffff0000u : ua << 16), y = __uint_as_float((k & 1) ? ub & 0xffff0000u : ub << 16);
                        zr[k] = fmaf(c.x, x, fmaf(c.z, y, zr[k]));
                        zi[k] = fmaf(c.y, x, fmaf(c.w, y, zi[k]));
                    }
                }
                const uint32_t dst = sb + OFF_P + u * 16384 + off;
#pragma unroll
                for (int k = 0; k < 16; k += 8) {
                    sts128(dst + k * 1024, pk(zr[k], zr[k + 1]), pk(zr[k + 2], zr[k + 3]), pk(zr[k + 4], zr[k + 5]), pk(zr[k + 6], zr[k + 7]));
                    sts128(dst + k * 1024 + 64, pk(zi[k], zi[k + 1]), pk(zi[k + 2], zi[k + 3]), pk(zi[k + 4], zi[k + 5]), pk(zi[k + 6], zi[k + 7]));
                }
                fence_async_sm();
                bar_sync(1, 256);
                if (tid == 0) mbar_arrive(bars + B_IN + u * 8);
                STAMPO(1, u);
            }
            return;
        }
        if (wg == 2 && !spare) {
            asm volatile("setmaxnreg.inc.sync.aligned.u32 176;");
            uint32_t f1[16];
            cf tw[8];
            if (TAB_T0) __nanosleep(TAB_T0);
            ldtab<4, 2048>(f1, TAB_F1 + t7 * 16);
            ldtab_cf<16>(tw, TAB_TW1 + (t7 >> 2) * 64);
            const uint32_t ep = get_epoch(bars);
            uint32_t a0 = sb + OFF_P + (8 * w + gl + 32 * (mi >> 1)) * 128 + (((((mi & 1) << 2) | (fpos & 3)) ^ gl) << 4);
            float acc[128];
            const uint64_t dx = opaque(mkdesc(sb + OFF_F, 4096, 512, 2));
            mbar_wait(bars + (P1H ? B_RAW : B_XIN), 0);
            pinu(f1);
            wg_fence();
#pragma unroll
            for (int j = 0; j < 4; j++) mma128_rs<0, 1>(acc, f1[4 * j], f1[4 * j + 1], f1[4 * j + 2], f1[4 * j + 3], dx + j * 64, j);
            if (P1H) { wg_commit(); mbar_wait(bars + B_XIN, 0); wg_fence(); }
            STAMP(20);
#pragma unroll
            for (int j = 0; j < 4; j++) mma128_rs<64, 1>(acc, f1[4 * j], f1[4 * j + 1], f1[4 * j + 2], f1[4 * j + 3], dx + 1024 + j * 64, j);
            wg_commit();
            wg_wait<0>();
            pin(acc);
            pinu(f1);
#pragma unroll 1
            for (int h = 0;; h++) {
                const uint32_t tmask = 2 * q + h == fpos >> 2 ? ~1u : ~0u, tbit = ep & ~tmask;
#pragma unroll
                for (int cl = 0; cl < 2; cl++) {
                    c2 v[8];
#pragma unroll
                    for (int n = 0; n < 8; n++) {
                        const int i = 4 * (4 * n + cl);
                        v[n] = {{acc[i], acc[i + 2]}, {acc[i + 1], acc[i + 3]}};
                    }
                    dft8<true, YP1>(v, tw);
#pragma unroll
                    for (int r = 0; r < 8; r += 2) {
                        uint32_t o0 = pk(v[r].a.x, v[r].b.x), o1 = pk(v[r].a.y, v[r].b.y), o2 = pk(v[r + 1].a.x, v[r + 1].b.x), o3 = pk(v[r + 1].a.y, v[r + 1].b.y);
                        if (cl == 0) { o0 = (o0 & tmask) | tbit; o2 = (o2 & tmask) | tbit; }
                        stsm4((a0 ^ (cl << 4)) + r * 4096, o0, o1, o2, o3);
                    }
                }
                if (h) break;
                a0 ^= 32;
#pragma unroll
                for (int n = 0; n < 8; n++) {
                    asm volatile("mov.b32 %0, %8; mov.b32 %1, %9; mov.b32 %2, %10; mov.b32 %3, %11; mov.b32 %4, %12; mov.b32 %5, %13; mov.b32 %6, %14; mov.b32 %7, %15; pmevent 1;"
                                 : "=&f"(acc[16 * n]), "=&f"(acc[16 * n + 1]), "=&f"(acc[16 * n + 2]), "=&f"(acc[16 * n + 3]), "=&f"(acc[16 * n + 4]), "=&f"(acc[16 * n + 5]), "=&f"(acc[16 * n + 6]), "=&f"(acc[16 * n + 7])
                                 : "f"(acc[16 * n + 8]), "f"(acc[16 * n + 9]), "f"(acc[16 * n + 10]), "f"(acc[16 * n + 11]), "f"(acc[16 * n + 12]), "f"(acc[16 * n + 13]), "f"(acc[16 * n + 14]), "f"(acc[16 * n + 15]));
                }
            }
            fence_async_sm();
            warp_arrive(bars + B_STGU);
            bar_sync(3, 128);
            asm volatile("setmaxnreg.dec.sync.aligned.u32 152;");
            bar_arrive(7, 256);
        }
        if (wg == 1) {
            if (LAM_T0) __nanosleep(LAM_T0);
            const int cl = tid & 127, ch = (cl >> 6) * 512 + ((cl >> 3) & 1) * 256 + cb * 32 + ((cl >> 4) & 3) * 8 + (cl & 7);
            const float lr = bf2f(*(const unsigned short*)padd(p.lre, 2 * ch)), li = bf2f(*(const unsigned short*)padd(p.lim, 2 * ch));
            const float dt = __bfloat162float(__float2bfloat16(expf(bf2f(*(const unsigned short*)padd(p.ldt, 2 * ch)))));
            const float an = dt * li, th = an * 0.318309873342514f;
            float sn, cs, inv;
            sincospif(fmaf(rintf(0.5f * th), -2.f, th) + fmaf(an, 1.2841276653e-8f, fmaf(an, 0.318309873342514f, -th)), &sn, &cs);
            const float ex = expf(dt * lr), br = ex * cs, bi = ex * sn;
            asm("rcp.approx.f32 %0, %1;" : "=f"(inv) : "f"(lr * lr + li * li));
            inv += inv;
            const float cr = ((br - 1.f) * lr + bi * li) * inv, ci = (bi * lr - (br - 1.f) * li) * inv;
            sts128(sb + OFF_LAM + cl * 16, __float_as_uint(br), __float_as_uint(-bi), __float_as_uint(cr), __float_as_uint(-ci));
            mbar_wait(bars + B_EP, 0);
            bar_sync(8, 128);
            if (tid == 128) mbar_arrive(bars + B_LAM);
        }
        if (wg != 2) {
        if (wg == 0) bar_sync(4, 128); else bar_sync(7, 256);
        asm volatile("setmaxnreg.inc.sync.aligned.u32 160;");
        if (wg == 0) bar_sync(4, 128);
        float d[128];
        STAMPW(0, 10);
        Ring rg = ring_at(sb, role * 66 + wg * 16);
        cf lam[2];
        unsigned ep;
        gemm1(d, rg, ring_desc(sb, 0, 16, 1), ring_desc(sb, 16384, 16, 1), wg);
        const uint32_t lama = sb + OFF_LAM + wg * 1024 + w * 256 + (fresh_lane() & 28) * 4;
        mbar_wait_fast(bars + B_LAM, 0);
        lam[0] = lds_cf(lama); lam[1] = lds_cf(lama + 128);
        asm volatile("ld.shared.u32 %0, [%1];" : "=r"(ep) : "r"(bars + B_EPOCH) : "memory");
        asm volatile("setmaxnreg.inc.sync.aligned.u32 176;");
        cf L[2] = {lam[0], lam[1]};
#pragma unroll
        for (int i = 0; i < 4; i++) { L[0] = csq(L[0]); L[1] = csq(L[1]); }
        asm volatile("" : "+f"(L[0].x), "+f"(L[0].y), "+f"(L[1].x), "+f"(L[1].y)::"memory");
        wg_wait<0>();
        ring_release(rg, 8 * wg);
        pin(d);
        STAMPW(1, 11);
        {
            const int lane = fresh_lane(), g = lane >> 2, q = lane & 3, mi = lane >> 3, gl = lane & 7;
            cf f[2], fb2[2];
#pragma unroll
            for (int i = 0; i < 17; i++) {
#pragma unroll
                for (int h = 0; h < 2; h++) {
                    const int r = 4 * (i >> 1) + 2 * h + (i & 1), r2 = 32 + 4 * ((i - 1) >> 1) + 2 * h + ((i - 1) & 1);
                    if (i < 16) f[h] = i ? cfma(lam[h], f[h], {d[r], -d[64 + r]}) : cf{d[r], -d[64 + r]};
                    if (i > 0) fb2[h] = i > 1 ? cfma(lam[h], fb2[h], {d[r2], -d[64 + r2]}) : cf{d[r2], -d[64 + r2]};
                    if (i && (h || !(YS & 8))) YIELD_S1();
                }
            }
            const uint8_t* cbase = (const uint8_t*)g_carry + (tc * 16 + wg * 8 + cb) * 512 + w * 64;
            const uint8_t* cptr = padd(cbase, g * 8);
            const unsigned tag = ep & 15u;
#pragma unroll
            for (int h = 0; h < 2; h++) { f[h] = cfma(L[h], f[h], fb2[h]); L[h] = csq(L[h]); }
            cf s0[2], s1[2], s2[2];
#pragma unroll
            for (int h = 0; h < 2; h++) {
                s0[h] = {__shfl_sync(~0u, f[h].x, 0, 4), __shfl_sync(~0u, f[h].y, 0, 4)};
                s1[h] = {__shfl_sync(~0u, f[h].x, 1, 4), __shfl_sync(~0u, f[h].y, 1, 4)};
                s2[h] = {__shfl_sync(~0u, f[h].x, 2, 4), __shfl_sync(~0u, f[h].y, 2, 4)};
            }
#pragma unroll
            for (int h = 0; h < 2; h++) {
                s1[h] = cfma(L[h], s0[h], s1[h]);
                s2[h] = cfma(L[h], s1[h], s2[h]);
                f[h] = cfma(L[h], s2[h], f[h]);
                asm volatile("{.reg .pred p; .reg .b64 a; setp.eq.u32 p, %3, 3; mov.b64 a, {%1,%2}; @p st.relaxed.gpu.global.b64 [%0], a;}" ::"l"(cptr + h * 256),
                             "r"((__float_as_uint(f[h].x) & ~15u) | tag), "f"(f[h].y), "r"(q) : "memory");
            }
            STAMPX(2, 12);
            cf gam = lds_cf(lama + 8);
            cf st = csel(q & 2, csel(q & 1, s2[0], s1[0]), csel(q & 1, s0[0], {0.f, 0.f}));
            const cf st1 = csel(q & 2, csel(q & 1, s2[1], s1[1]), csel(q & 1, s0[1], {0.f, 0.f}));
            cptr = padd(cbase - 4 * 8192, (3 - mi) * 8192 + gl * 8);
            const int nprev = tc - 1 - mi;
            const uint8_t* hptr = padd(g_H + (size_t)(tc * 32 + wg * 16 + (cb & 6)) * 16384 + ((cb & 1) * 4 + w) * 1024, g * 64 + ((q ^ (g >> 1)) << 4));
            const uint32_t hm = 4 * (g & 1) + (q ^ (g >> 1)) == (cb & 1) * 4 + w ? ~1u : ~0u;
            float u[64];
            uint64_t fv[4] = {tag, tag, tag, tag};
            prescale<0>(u, d, gam);
            gather(fv, cptr, nprev);
#pragma unroll 1
            for (int h = 0;; h++) {
                const cf L2 = csq(L[0]), M = csq(L2);
                cf M4 = csq(csq(M));
                M4 = {__shfl_sync(~0u, M4.x, 4 * gl), __shfl_sync(~0u, M4.y, 4 * gl)};
                cf lq = cmul(gam, cmul(csel(q & 1, L[0], {1.f, 0.f}), csel(q & 2, L2, {1.f, 0.f})));
                st = cmul(gam, st);
                asm volatile("pmevent 1;" : "+f"(lq.x), "+f"(lq.y), "+f"(st.x), "+f"(st.y));
#pragma unroll 1
                for (unsigned n = 0; __any_sync(~0u, (((uint32_t)fv[0] ^ tag) | ((uint32_t)fv[1] ^ tag) | ((uint32_t)fv[2] ^ tag) | ((uint32_t)fv[3] ^ tag)) & 15u) && n < SPIN_LIMIT; n++) gather(fv, cptr, nprev);
                if (!h) STAMPX(53, 54);
                cf P = as_cf(fv[3]), pj[4];
#pragma unroll
                for (int a = 2; a >= 0; a--) P = cfma(M4, P, as_cf(fv[a]));
                cptr += 256;
                asm volatile("" : "+f"(P.x), "+f"(P.y)::"memory");
                gather(fv, cptr, h ? -1 : nprev);
#pragma unroll
                for (int j = 3; j >= 0; j--) pj[j] = {__shfl_sync(~0u, P.x, g + 8 * j), __shfl_sync(~0u, P.y, g + 8 * j)};
                st = cfma(lq, cfma(M, cfma(M, cfma(M, pj[3], pj[2]), pj[1]), pj[0]), st);
                if (!h) STAMPX(3, 13);
                uint32_t keep = sb >> 28;
                scan2(u, lam[0], st, hptr, hm, ep & ~hm, keep);
                warp_arrive(bars + B_HOWN + wg * 16 + h * 8 + keep);
                if (h) break;
                STAMPW(4, 14);
                if (wg == 1 && nu) bar_sync(9, 256);
                lds128f(lama + 128, lam[0].x, lam[0].y, gam.x, gam.y);
                st = st1;
                L[0] = L[1];
                hptr += 8 * 16384;
                prescale<1>(u, d, gam);
            }
            STAMPW(5, 15);
        }
        if (wg == 0) bar_sync(4, 128); else bar_sync(8, 128);
        if (wg == 0) {
            asm volatile("setmaxnreg.dec.sync.aligned.u32 160;");
            float y[128];
            rg = ring_at(sb, role * 66 + 32);
            STAMP(6);
            STAMP(7);
            const uint64_t dA = ring_desc(sb, 0, 512, 2), dB = ring_desc(sb, 16384, 16, 1);
            gemm2(y, rg, dA, dB, 0);
            asm volatile("setmaxnreg.inc.sync.aligned.u32 184;");
            const int lane = fresh_lane(), g = lane >> 2, q = lane & 3;
            const int pg = 2 * (g & 3) + (g >> 2);
            float* op = (float*)padd(p.out + (size_t)(tc * 128 + 64 * (w & 1) + 8 * (w >> 1)) * 2048 + 1024 + cb * 128, pg * 8192 + q * 16);
            const uint32_t xa = sb + OFF_F + (16 * (w & 1) + 8 * (w >> 1) + pg) * 128 + (((q >> 1) ^ pg) << 4) + (q & 1) * 8;
#define HALF0(k) wg_fence(); peek(k < 63 ? rg.full + SL(k + 1) * 8 : bars + B_XD, PH(k + 1)); half_step<0, k>(y, dA, dB); wg_commit(); peek_wait(k < 63 ? rg.full + SL(k + 1) * 8 : bars + B_XD, PH(k + 1), rg.n);
            HALF0(60) HALF0(61) HALF0(62) HALF0(63)
            const uint64_t dB2 = ring_desc(sb >> 1, 16384, 16, 1);
            uint32_t xa0[8], xa1[8], dd[16];
#pragma unroll
            for (int i = 0; i < 8; i++) asm volatile("ld.shared.v2.b32 {%0,%1}, [%2];" : "=r"(dd[2 * i]), "=r"(dd[2 * i + 1]) : "r"(sb + OFF_LAM + q * 8 + 32 * i) : "memory");
            load_x4<0, 0>(xa0, xa);
            wg_fence();
            half_step<64, 64 - SKEW>(y, dA, dB2);
            wg_commit();
            wg_wait<1>();
#pragma unroll
            for (int i = 0; i < 64; i++) asm volatile("" : "+f"(y[i])::"memory");
            STAMP(16);
#define M1(n) if (4 + (n) < 4 * SKEW) mma_h<64, 65 - SKEW + (n) / 4, (n) % 4>(y, dA, dB2);
#define MM(n) if (4 + (n) / 2 * MPP < 4 * SKEW) { if (MPY) YIELD(); wg_fence(); M1((n) / 2 * MPP) M1((n) / 2 * MPP + 1) if (MPP > 2) { M1((n) / 2 * MPP + 2) } }
#define OUT4(R, U, X, n) out_piece<R, U>(y, dd, X[0], X[1], op); MM(n) out_piece<R, U + 1>(y, dd, X[2], X[3], op); MM(n + 2) \
                         out_piece<R, U + 2>(y, dd, X[4], X[5], op); MM(n + 4) out_piece<R, U + 3>(y, dd, X[6], X[7], op); MM(n + 6)
            load_x4<0, 4>(xa1, xa);
            OUT4(0, 0, xa0, 0)
            load_x4<1, 0>(xa0, xa);
            OUT4(0, 4, xa1, 8)
            wg_commit();
            load_x4<1, 4>(xa1, xa);
            OUT4(1, 0, xa0, 16)
            load_x4<2, 0>(xa0, xa);
            OUT4(1, 4, xa1, 16)
            STAMP(18);
            wg_wait<0>();
#pragma unroll
            for (int i = 64; i < 128; i++) asm volatile("" : "+f"(y[i])::"memory");
            STAMP(8);
            load_x4<2, 4>(xa1, xa);
            mbar_wait_fast(bars + B_XD + 8, 0);
            OUT4(2, 0, xa0, 16)
            load_x4<3, 0>(xa0, xa);
            OUT4(2, 4, xa1, 16)
            load_x4<3, 4>(xa1, xa);
            OUT4(3, 0, xa0, 16)
            OUT4(3, 4, xa1, 16)
            STAMP(9);
            return;
        }
        asm volatile("setmaxnreg.dec.sync.aligned.u32 152;");
        } else {
        if (nu) {
            constexpr int Y = YP2;
            cf T[8];
            ldtab_cf<2048>(T, TAB_T + t7 * 16);
            const uint32_t ep = get_epoch(bars);
            const int ka = pos_of(t7 >> 2);
            asm volatile("setp.eq.u32 p0, %0, 0;" ::"r"(__shfl_sync(~0u, t7, lane)));
            mbar_wait(bars + B_WSP, 0);
            mbar_wait(bars + B_FG, 0);
            uint32_t wd[4], wm[4], vo[32];
            const uint8_t* vp;
            int slot;
            const int kap0 = unit_of(role, 0, slot), al = 2 * kap0;
            const int kap1 = __shfl_sync(~0u, unit_of(role, 1, slot), 0);
            slot = __shfl_sync(~0u, slot, 0);
            cf be1 = twid(kap0 + 512 * q, 2048), be2 = csq(be1), be3 = cmul(be1, be2);
#pragma unroll
            for (int j = 0; j < 4; j++) {
                wd[j] = sb + OFF_WD + ((j + q) & 3) * WPITCH + (al & 15) + 2 * ka + 64 * q;
                wm[j] = sb + OFF_WM + (((role ? 3 : 4) - j - q) & 3) * WPITCH + (-al & 15) + 1024 - 2 * ka - 64 * q;
                wd[j] = __shfl_sync(~0u, wd[j], lane);
            }
#pragma unroll 1
            for (int u = 0; u < nu; u++) {
                const uint32_t buf = sb + OFF_P + u * 16384;
                float acc[64], za[32], zb[32], ya[32], yb[32], vv[64];
                const uint64_t dF = opaque(mkdesc(sb + OFF_F, 16, 1024, 1)), dB = opaque(mkdesc(buf, 4096, 512, 2));
                mbar_wait(bars + B_IN + u * 8, 0);
                if (!role) {
                    const uint32_t z = buf + w * 1024 + (fresh_lane() >> 2) * 128 + 64 + (fresh_lane() & 3) * 16;
#pragma unroll
                    for (int i = 0; i < 4; i++) sts128(z + i * 4096, 0, 0, 0, 0);
                    fence_async_sm();
                    bar_sync(3, 128);
                }
                STAMP3(22);
                wg_fence();
#pragma unroll
                for (int j = 0; j < 4; j++) mma128_ss<0, 0, 1>(acc, dF + j * 2, dB + j * 64, j);
                wg_commit();
                if (u) {
                    const uint32_t va = sb + OFF_P + (((uint32_t)(uintptr_t)vp - (uint32_t)(uintptr_t)g_X) >> 9 & 0x7c0) + ((uint32_t)(uintptr_t)vp & 31) + (fresh_lane() & 4) * 8;
                    bar_sync(3, 128);
#pragma unroll
                    for (int k = 0; k < 16; k++) sts64(va + ((k >> 1) & 1) * 8192 + (k >> 2) * 2048 + (k & 1) * 256, vo[2 * k], vo[2 * k + 1]);
                    fence_async_sm();
                    warp_arrive(bars + B_STG);
                    if (!role) { const uint32_t t = wm[0]; wm[0] = wm[1]; wm[1] = wm[2]; wm[2] = wm[3]; wm[3] = t; }
                }
                STAMP3(39);
                wg_wait<0>();
                pin(acc);
                STAMP3(30);
                uint32_t af[16], ag[16];
#pragma unroll
                for (int k = 0; k < 8; k++) {
                    uint32_t(&o)[16] = k < 4 ? af : ag;
                    const int c = k & 3;
#pragma unroll
                    for (int b = 0; b < 2; b++) {
                        const int i = 4 * (4 * ((k >> 2) * 2 + b) + c);
                        c2 x = mul2(c2{{acc[i], acc[i + 2]}, {acc[i + 1], acc[i + 3]}}, c2{T[2 * c], T[2 * c + 1]});
                        fin<(YT >> 1)>(x);
                        o[4 * c + b] = pk(x.a.x, x.a.y);
                        o[4 * c + 2 + b] = pk(x.b.x, x.b.y);
                    }
                    asm volatile("" : "+r"(o[4 * c]), "+r"(o[4 * c + 1]), "+r"(o[4 * c + 2]), "+r"(o[4 * c + 3])::"memory");
                    wg_fence();
                    mma64_rs<0>(k < 4 ? za : zb, o[4 * c], o[4 * c + 1], o[4 * c + 2], o[4 * c + 3], dF + c * 2, c);
                    if ((YT & 1) && k < 7) YIELD();
                }
                wg_commit();
                STAMP3(31);
                mbar_wait(bars + B_WD, u & 1);
                uint32_t wr[16];
#pragma unroll
                for (int i = 0; i < 16; i++) wr[i] = lds16(wd[i >> 2] + 256 * ((i >> 1) & 1) + (i & 1) * 4 * WPITCH);
                wg_wait<0>();
                pin(za);
                pin(zb);
                pinu(af);
                pinu(ag);
                STAMP3(32);
#pragma unroll
                for (int jb = 0; jb < 4; jb++) {
                    const int i = 8 * jb;
                    c2 s0 = {{za[i], za[i + 4]}, {za[i + 1], za[i + 5]}}, s2 = {{za[i + 2], za[i + 6]}, {za[i + 3], za[i + 7]}};
                    c2 s1 = {{zb[i], zb[i + 4]}, {zb[i + 1], zb[i + 5]}}, s3 = {{zb[i + 2], zb[i + 6]}, {zb[i + 3], zb[i + 7]}};
                    s2 = mul2(s2, be1);
                    fin<Y>(s2);
                    bfly_tw<Y>(s0, s1, be2, s2, s3, be3);
                    bfly<Y>(s0, s2); bfly_mi<Y>(s1, s3);
                    c2 W[4];
#pragma unroll
                    for (int j = 0; j < 4; j++) {
                        W[j] = {{__uint_as_float(wr[4 * j] << 16), __uint_as_float(wr[4 * j + 1] << 16)}, {__uint_as_float(wr[4 * j + 2] << 16), __uint_as_float(wr[4 * j + 3] << 16)}};
                        if ((jb & 1) == 0)
                            asm volatile("@p0 ld.shared.v2.f32 {%0,%1}, [%2];" : "+f"(W[j].a.x), "+f"(W[j].a.y) : "r"(sb + OFF_WSP + u * 64 + jb * 16 + j * 8));
                    }
                    if (jb < 3) {
#pragma unroll
                        for (int k = 0; k < 16; k++) {
                            const int e = (k >> 1) & 1, pl = (k & 1) * 4 * WPITCH;
                            wr[k] = jb == 0 ? lds16(wd[k >> 2] + 512 + 256 * e + pl) : lds16(wm[k >> 2] - 512 * (jb - 1) - 256 * e + pl);
                        }
                    }
                    if (jb >= 2) {
#pragma unroll
                        for (int j = 0; j < 4; j++) { W[j].a.y = -W[j].a.y; W[j].b.y = -W[j].b.y; }
                    }
                    s0 = mul2(s0, W[0]); fin<Y>(s0);
                    s1 = mul2(s1, W[1]); fin<Y>(s1);
                    bfly_tw<Y>(s0, s2, W[2], s1, s3, W[3]);
                    bfly<Y>(s0, s1); bfly_mi<Y>(s2, s3);
                    af[4 * jb] = pk(s0.a.x, s0.b.x); af[4 * jb + 1] = pk(s3.a.x, s3.b.x); af[4 * jb + 2] = pk(s0.a.y, s0.b.y); af[4 * jb + 3] = pk(s3.a.y, s3.b.y);
                    ag[4 * jb] = pk(s1.a.x, s1.b.x); ag[4 * jb + 1] = pk(s2.a.x, s2.b.x); ag[4 * jb + 2] = pk(s1.a.y, s1.b.y); ag[4 * jb + 3] = pk(s2.a.y, s2.b.y);
                }
                pinu(af);
                pinu(ag);
                warp_arrive(bars + B_WFREE);
                wg_fence();
#pragma unroll
                for (int j = 0; j < 4; j++) mma64_rs<1>(ya, af[4 * j], af[4 * j + 1], af[4 * j + 2], af[4 * j + 3], dF + j * 128, j);
                wg_commit();
#pragma unroll
                for (int j = 0; j < 4; j++) mma64_rs<1>(yb, ag[4 * j], ag[4 * j + 1], ag[4 * j + 2], ag[4 * j + 3], dF + j * 128, j);
                wg_commit();
                STAMP3(33);
                {
                    const uint32_t a0 = buf + (mi & 1) * 4096 + (16 * w + 8 * (mi >> 1) + gl) * 64 + ((gl >> 1) << 4);
#pragma unroll
                    for (int h = 0; h < 2; h++) {
                        if (h == 0) { wg_wait<1>(); pin(ya); pinu(af); STAMP3(34); } else { wg_wait<0>(); pin(yb); pinu(ag); }
                        const float(&yy)[32] = h ? yb : ya;
#pragma unroll
                        for (int c = 0; c < 4; c++) {
                            const int i = 8 * ((c + 2 * h) & 3), k = 8 * ((c + 2 * h + 1) & 3) + 2;
                            c2 x = {cmulc({yy[i], yy[i + 1]}, T[2 * c]), cmulc({yy[k], yy[k + 1]}, T[2 * c])};
                            fin<YI & 1>(x);
                            c2 y = {cmulc({yy[i + 4], yy[i + 5]}, T[2 * c + 1]), cmulc({yy[k + 4], yy[k + 5]}, T[2 * c + 1])};
                            fin<(YI >> 1)>(y);
                            stsm4((a0 ^ (c << 4)) + h * 8192, pk(x.a.x, y.a.x), pk(x.b.x, y.b.x), pk(x.a.y, y.a.y), pk(x.b.y, y.b.y));
                        }
                    }
                }
                STAMP3(38);
                fence_async_sm();
                bar_sync(3, 128);
                wg_fence();
#pragma unroll
                for (int j = 0; j < 4; j++) mma128_ss<0, 1, 1>(vv, dF + j * 128, dB + j * 64, j);
                wg_commit();
                STAMP3(35);
                if (u && !spare) bar_arrive(9, 256);
                const int lane = fresh_lane(), g = lane >> 2, q = lane & 3;
                vp = padd(g_X + (4 << 20) + w * (8 * 32768) + (role ? u : 1) * 16384 + slot * 64,
                                         (g >> 1) * 32768 + (role ? g & 1 : u) * 32 + (((q ^ (slot >> 1)) & 1) << 4) + (q >> 1) * 8);
                const uint32_t tmask = (((g & 1) == ((slot >> 3) & 1) || !role) && q == ((slot >> 1) & 2)) ? ~1u : ~0u, tbit = (ep ^ (role + u ? 0 : g)) & ~tmask;
                be1 = twid(kap1 + 512 * q, 2048); be2 = csq(be1); be3 = cmul(be1, be2);
                asm volatile("pmevent 1;" : "+f"(be1.x), "+f"(be1.y), "+f"(be2.x), "+f"(be2.y), "+f"(be3.x), "+f"(be3.y), "+l"(vp)::"memory");
                wg_wait<0>();
                pin(vv);
                STAMP3(36);
#pragma unroll
                for (int k = 0; k < 16; k++) {
                    const int i = 8 * (k >> 1) + 2 * (k & 1);
                    vo[2 * k] = (pk(vv[i], vv[i + 1]) & tmask) | tbit;
                    vo[2 * k + 1] = pk(vv[i + 4], vv[i + 5]);
                }
                pinu(vo);
            }
            if (!role) mbar_wait(bars + B_IN + 16, 0);
            warp_arrive(bars + B_STG);
            const bool odd = fresh_lane() & 4;
            if (!VPOS) hint_v(g_cnt + 32 + nu * 32, 1);
            store_v<0, 4>(vo, vp, role || !odd);
            if (VPOS) hint_v(g_cnt + 32 + nu * 32, 1);
            store_v<4, 16>(vo, vp, role || odd);
        }
        if (spare) return;
        }
        {
            constexpr int Y = YP3;
            uint32_t sp[8];
            cf tw[8];
            ldtab<2, 2048>(sp, TAB_SP + fb * 4096 + t7 * 16);
            ldtab_cf<16>(tw, TAB_TW3 + fb * 2048 + (t7 >> 2) * 64);
            const uint64_t dF = opaque(mkdesc(sb + OFF_F, 16, 1024, 1)), dB = opaque(mkdesc(sb + OFF_P + hf * 8192, 1024, 256, 3));
            const uint8_t* op = padd(p.out + (1024 + fb) * 2048 + fcb * 32 + hf * 16, (t7 >> 2) * 32768 + (q >> 1) * 16 + (q & 1) * 32);
            float acc[64], out[64];
            mbar_wait(bars + B_IN + 24, 0);
            mbar_wait(bars + B_FG, 1);
            STAMP(25);
            pinu(sp);
            wg_fence();
#pragma unroll
            for (int j = 0; j < 4; j++) {
                const uint64_t db = dB + (j >> 1) * 1024 + (j & 1) * 32;
                mma112_ss(acc, dF + j * 2, db + 64, j);
                if (j & 1) mma16_rs(acc, 0u, sp[2 * j], 0u, sp[2 * j + 1], db, 1);
                else mma16_rs(acc, sp[2 * j], 0u, sp[2 * j + 1], 0u, db, j);
            }
            wg_commit();
            wg_wait<0>();
            pin(acc);
            pinu(sp);
            warp_arrive(bars + B_P3M);
            if (STAG && !hf) bar_sync(5, 256);
#pragma unroll
            for (int cl = 0; cl < 2; cl++) {
                c2 z[8];
#pragma unroll
                for (int n = 0; n < 8; n++) {
                    const int i = 4 * (2 * n + cl);
                    z[n] = {{acc[i], acc[i + 2]}, {acc[i + 1], acc[i + 3]}};
                }
                z[0] = {{z[0].a.x + z[0].a.y, z[0].a.x - z[0].a.y}, {z[0].b.x + z[0].b.y, z[0].b.x - z[0].b.y}};
                z[4] = mul2(z[4], tw[4]);
                fin<Y>(z[0], z[4]);
#pragma unroll
                for (int n = 1; n < 4; n++) {
                    const cf iw = n == 1 ? cf{0.38268343236508977f, 0.92387953251128674f}
                                         : (n == 2 ? cf{0.70710678118654752f, 0.70710678118654752f} : cf{0.92387953251128674f, 0.38268343236508977f});
                    c2 y = mul2(z[n], tw[n]);
                    fin<Y>(y);
                    const cf t = {tw[8 - n].x, -tw[8 - n].y};
                    c2 E = fma2(c2{{z[8 - n].a.x, -z[8 - n].a.y}, {z[8 - n].b.x, -z[8 - n].b.y}}, t, y);
                    fin<Y>(E);
                    z[n] = fma2(twm2(y, E), iw, E);
                    fin<Y>(z[n]);
                    z[8 - n] = {{fmaf(2.f, E.a.x, -z[n].a.x), fmaf(-2.f, E.a.y, z[n].a.y)}, {fmaf(2.f, E.b.x, -z[n].b.x), fmaf(-2.f, E.b.y, z[n].b.y)}};
                }
                dft8<false, Y>(z, tw);
#pragma unroll
                for (int m = 0; m < 8; m++) {
                    out[8 * m + 2 * cl] = z[m].a.x; out[8 * m + 2 * cl + 1] = z[m].b.x;
                    out[8 * m + 4 + 2 * cl] = z[m].a.y; out[8 * m + 5 + 2 * cl] = z[m].b.y;
                }
            }
            pin(out);
            if (STAG) { if (hf) bar_arrive(5, 256); else if (STAG > 1) bar_sync(6, 256); }
            if (hf) STAMP(26);
#pragma unroll
            for (int m = 0; m < 16; m++) {
                asm volatile("st.global.v4.f32 [%0], {%1,%2,%3,%4};" ::"l"(op + (m - 8) * (1 << 20)), "f"(out[4 * m]), "f"(out[4 * m + 1]), "f"(out[4 * m + 2]), "f"(out[4 * m + 3]) : "memory");
                if (PACE_O && m < 15 && m % PACE_ON == PACE_ON - 1)
                    asm volatile("{.reg .pred p; mbarrier.test_wait.parity.shared::cta.b64 p, [%0], 0; @!p nanosleep.u32 %1;}" ::"r"(bars + B_DONE), "n"(PACE_O) : "memory");
            }
            if (STAG > 1 && hf) bar_arrive(6, 256);
            STAMP(27);
        }
    }
}

typedef CUresult (*EncodeFn)(CUtensorMap*, CUtensorMapDataType, cuuint32_t, void*, const cuuint64_t*, const cuuint64_t*, const cuuint32_t*,
                             const cuuint32_t*, CUtensorMapInterleave, CUtensorMapSwizzle, CUtensorMapL2promotion, CUtensorMapFloatOOBfill);

static CUtensorMap make_map(EncodeFn enc, const void* ptr, int rank, const cuuint64_t* dims, const cuuint64_t* strides, const cuuint32_t* box,
                            CUtensorMapSwizzle swz, CUtensorMapL2promotion promo, CUtensorMapDataType dt = CU_TENSOR_MAP_DATA_TYPE_BFLOAT16) {
    CUtensorMap m;
    const cuuint32_t es[5] = {1, 1, 1, 1, 1};
    enc(&m, dt, rank, const_cast<void*>(ptr), dims, strides, box, es, CU_TENSOR_MAP_INTERLEAVE_NONE, swz, promo,
        CU_TENSOR_MAP_FLOAT_OOB_FILL_NONE);
    return m;
}

extern "C" void kernel_launch(void* const* d_in, const int* in_sizes, int n_in, void* d_out, int out_size) {
    void* fn = nullptr;
    cudaDriverEntryPointQueryResult qr;
    cudaGetDriverEntryPoint("cuTensorMapEncodeTiled", &fn, cudaEnableDefault, &qr);
    EncodeFn enc = (EncodeFn)fn;
    void* pX;
    cudaGetSymbolAddress(&pX, g_X);
    const CUtensorMapL2promotion P256 = CU_TENSOR_MAP_L2_PROMOTION_L2_256B, P0 = CU_TENSOR_MAP_L2_PROMOTION_NONE;

    const cuuint64_t dX[5] = {1024, 2, 4, 16, 16}, sX[4] = {2048, 32 * 2048, 2 * 2048, 128 * 2048};
    const cuuint32_t bX[5] = {64, 2, 4, 16, 1};
    CUtensorMap tmX = make_map(enc, d_in[3], 5, dX, sX, bX, CU_TENSOR_MAP_SWIZZLE_128B, P256);
    const cuuint64_t dXd[4] = {64, 2048, 2, 16}, sXd[3] = {2048, 64 * 2048, 128};
    const cuuint32_t bXd[4] = {64, 16, 2, 2};
    CUtensorMap tmXd = make_map(enc, d_in[3], 4, dXd, sXd, bXd, CU_TENSOR_MAP_SWIZZLE_128B, P256);
    const cuuint64_t dB[4] = {1024, 8, 4, 32}, sB[3] = {2048, 256 * 2048, 8 * 2048};
    const cuuint32_t bB4[4] = {64, 8, 2, 4};
    CUtensorMap tmBre = make_map(enc, d_in[6], 4, dB, sB, bB4, CU_TENSOR_MAP_SWIZZLE_128B, P256);
    CUtensorMap tmBim = make_map(enc, d_in[7], 4, dB, sB, bB4, CU_TENSOR_MAP_SWIZZLE_128B, P256);
    const cuuint64_t dC[5] = {1024, 2, 4, 2, 64}, sC[4] = {2048, 4 * 2048, 2 * 2048, 16 * 2048};
    const cuuint32_t bC[5] = {64, 2, 4, 2, 4};
    CUtensorMap tmCre = make_map(enc, d_in[8], 5, dC, sC, bC, CU_TENSOR_MAP_SWIZZLE_128B, P256);
    CUtensorMap tmCim = make_map(enc, d_in[9], 5, dC, sC, bC, CU_TENSOR_MAP_SWIZZLE_128B, P256);

    const cuuint64_t dU[2] = {8192, 256}, sU[1] = {16384};
    const cuuint32_t bU[2] = {64, 64};
    CUtensorMap tmUst = make_map(enc, pX, 2, dU, sU, bU, CU_TENSOR_MAP_SWIZZLE_128B, P0);
    const cuuint64_t dV[2] = {16384, 128}, sV[1] = {32768};
    const cuuint32_t bV[2] = {32, 128};
    CUtensorMap tmVst = make_map(enc, (uint8_t*)pX + (4 << 20), 2, dV, sV, bV, CU_TENSOR_MAP_SWIZZLE_NONE, P0);
    const cuuint64_t dF[2] = {512 * 1026 / 8, 4}, sF[1] = {512 * 1026};
    const cuuint32_t bF[2] = {WPITCH / 8, 4};
    CUtensorMap tmWr = make_map(enc, d_in[1], 2, dF, sF, bF, CU_TENSOR_MAP_SWIZZLE_NONE, P0, CU_TENSOR_MAP_DATA_TYPE_UINT64);
    CUtensorMap tmWi = make_map(enc, d_in[2], 2, dF, sF, bF, CU_TENSOR_MAP_SWIZZLE_NONE, P0, CU_TENSOR_MAP_DATA_TYPE_UINT64);

    const cuuint64_t dA[3] = {1024, 64, 32}, sA[2] = {32 * 2048, 2048};
    const cuuint32_t bA[3] = {32, 64, 1};
    CUtensorMap tmXa = make_map(enc, d_in[0], 3, dA, sA, bA, CU_TENSOR_MAP_SWIZZLE_64B, XA_PROMO);

    Params p;
    p.wr = (const __nv_bfloat16*)d_in[1];
    p.wi = (const __nv_bfloat16*)d_in[2];
    p.lre = (const __nv_bfloat16*)d_in[4];
    p.lim = (const __nv_bfloat16*)d_in[5];
    p.ldt = (const __nv_bfloat16*)d_in[10];
    p.dsk = (const __nv_bfloat16*)d_in[11];
    p.out = (float*)d_out;
    int dev = 0, sms = 0;
    cudaGetDevice(&dev);
    cudaDeviceGetAttribute(&sms, cudaDevAttrMultiProcessorCount, dev);
    auto kernel = sms == 132 ? fused_kernel<true> : fused_kernel<false>;
    cudaFuncSetAttribute(kernel, cudaFuncAttributeMaxDynamicSharedMemorySize, SMEM_BYTES);
    kernel<<<132, 512, SMEM_BYTES>>>(tmX, tmBre, tmBim, tmCre, tmCim, tmXd, tmUst, tmVst, tmWr, tmWi, tmXa, p);
}
```

```cpp
#include <cuda_runtime.h>
#include <cuda.h>
#include <cuda_bf16.h>
#include <stdint.h>

#define NST 5
#define WPITCH 1056
#define OFF_P (NST * 32768)
#define OFF_F (OFF_P + 32768)
#define OFF_WD (OFF_F + 8192)
#define OFF_WM (OFF_WD + 8 * WPITCH)
#define OFF_BAR (OFF_F + 32768)
#define OFF_LAM (OFF_BAR + 432)
#define OFF_WSP (OFF_LAM + 2048)
#define OFF_PROF (OFF_WSP + 128)
#define SMEM_BYTES OFF_PROF
#define B_FULL 0
#define B_HL 40
#define B_EP 120
#define B_HR 128
#define B_XD 144
#define B_FG 160
#define B_WSP 168
#define B_WD 176
#define B_DONE 184
#define B_LD 192
#define B_RAW 200
#define B_LAM 208
#define B_IN 216
#define B_XIN 248
#define B_EMPTY 256
#define B_STG 320
#define B_WFREE 328
#define B_HOWN 336
#define B_STGU 368
#define B_P3M 384
#define B_EPOCH 416

#define XA_PACE 200
#define PACE_O 200
#define PACE_ON 2
#define TAB_T0 500
#define LAM_T0 1000
#define XA_N0 2
#define PACE_X 200
#define SKEW 4
#define SPIN_LIMIT (1u << 15)

__device__ __align__(1024) uint8_t g_X[8 << 20];
__device__ __align__(1024) uint8_t g_H[8 << 20];
__device__ __align__(1024) uint4 g_carry[16 * 512];
__device__ __align__(128) unsigned g_cnt[128];
__device__ __align__(128) unsigned g_epoch[132 * 8];

#define STAMP(i) do { } while (0)
#define STAMPO(i, o) do { } while (0)
#define STAMPW(a, b) do { } while (0)
#define STAMPX(a, b) do { } while (0)
#define STAMP5(i) do { } while (0)
#define STAMP3(i) do { } while (0)

#define TAB_FG 0
#define TAB_G 8192
#define TAB_F1 40960
#define TAB_T 49152
#define TAB_SP 57344
#define TAB_TW1 73728
#define TAB_TW3 75776
#define TAB_PC 83968
__device__ __align__(1024) const uint32_t g_tab[21248] = {
0x80003d80,0x80003d80,0x80003d80,0x80003d80,0x80003d80,0x80003d80,0x80003d80,0x80003d80,0x80003d80,0x80003d80,0x80003d80,0x80003d80,0x80003d80,0x80003d80,0x80003d80,0x80003d80,
0x80003d80,0x80003d80,0x80003d80,0x80003d80,0x80003d80,0x80003d80,0x80003d80,0x80003d80,0x80003d80,0x80003d80,0x80003d80,0x80003d80,0x80003d80,0x80003d80,0x80003d80,0x80003d80,
0x3d353d35,0x3d35bd35,0xbd35bd35,0xbd353d35,0x80003d80,0x3d800000,0x8000bd80,0xbd800000,0x3d353d35,0x3d35bd35,0xbd35bd35,0xbd353d35,0x80003d80,0x3d800000,0x8000bd80,0xbd800000,
0x3d353d35,0x3d35bd35,0xbd35bd35,0xbd353d35,0x80003d80,0x3d800000,0x8000bd80,0xbd800000,0x3d353d35,0x3d35bd35,0xbd35bd35,0xbd353d35,0x80003d80,0x3d800000,0x8000bd80,0xbd800000,
0x3d800000,0x3d6dbcc4,0x3d35bd35,0x3cc4bd6d,0x3d7bbc48,0x3d55bd0e,0x3d0ebd55,0x3c48bd7b,0x80003d80,0x3cc43d6d,0x3d353d35,0x3d6d3cc4,0x3c483d7b,0x3d0e3d55,0x3d553d0e,0x3d7b3c48,
0xbd800000,0xbd6d3cc4,0xbd353d35,0xbcc43d6d,0xbd7b3c48,0xbd553d0e,0xbd0e3d55,0xbc483d7b,0x8000bd80,0xbcc4bd6d,0xbd35bd35,0xbd6dbcc4,0xbc48bd7b,0xbd0ebd55,0xbd55bd0e,0xbd7bbc48,
0x3d0ebd55,0xbd7bbc48,0x3c483d7b,0x3d55bd0e,0x3d800000,0xbcc4bd6d,0xbd353d35,0x3d6d3cc4,0x3d553d0e,0x3c48bd7b,0xbd7b3c48,0x3d0e3d55,0x80003d80,0x3d6dbcc4,0xbd35bd35,0xbcc43d6d,
0xbd0e3d55,0x3d7b3c48,0xbc48bd7b,0xbd553d0e,0xbd800000,0x3cc43d6d,0x3d35bd35,0xbd6dbcc4,0xbd55bd0e,0xbc483d7b,0x3d7bbc48,0xbd0ebd55,0x8000bd80,0xbd6d3cc4,0x3d353d35,0x3cc4bd6d,
0x80003d80,0x3d353d35,0x3d800000,0x3d35bd35,0x3cc43d6d,0x3d6d3cc4,0x3d6dbcc4,0x3cc4bd6d,0x8000bd80,0xbd35bd35,0xbd800000,0xbd353d35,0xbcc4bd6d,0xbd6dbcc4,0xbd6d3cc4,0xbcc43d6d,
0x80003d80,0x3d353d35,0x3d800000,0x3d35bd35,0x3cc43d6d,0x3d6d3cc4,0x3d6dbcc4,0x3cc4bd6d,0x8000bd80,0xbd35bd35,0xbd800000,0xbd353d35,0xbcc4bd6d,0xbd6dbcc4,0xbd6d3cc4,0xbcc43d6d,
0x3d6d3cc4,0xbcc4bd6d,0xbcc43d6d,0x3d6dbcc4,0x80003d80,0x3d35bd35,0xbd800000,0x3d353d35,0xbd6dbcc4,0x3cc43d6d,0x3cc4bd6d,0xbd6d3cc4,0x8000bd80,0xbd353d35,0x3d800000,0xbd35bd35,
0x3d6d3cc4,0xbcc4bd6d,0xbcc43d6d,0x3d6dbcc4,0x80003d80,0x3d35bd35,0xbd800000,0x3d353d35,0xbd6dbcc4,0x3cc43d6d,0x3cc4bd6d,0xbd6d3cc4,0x8000bd80,0xbd353d35,0x3d800000,0xbd35bd35,
0x3d800000,0x3cc4bd6d,0xbd35bd35,0xbd6d3cc4,0x3d55bd0e,0xbc48bd7b,0xbd7bbc48,0xbd0e3d55,0x8000bd80,0xbd6dbcc4,0xbd353d35,0x3cc43d6d,0xbd0ebd55,0xbd7b3c48,0xbc483d7b,0x3d553d0e,
0xbd800000,0xbcc43d6d,0x3d353d35,0x3d6dbcc4,0xbd553d0e,0x3c483d7b,0x3d7b3c48,0x3d0ebd55,0x80003d80,0x3d6d3cc4,0x3d35bd35,0xbcc4bd6d,0x3d0e3d55,0x3d7bbc48,0x3c48bd7b,0xbd55bd0e,
0x3c48bd7b,0xbd0e3d55,0x3d55bd0e,0xbd7b3c48,0x3d800000,0xbd6dbcc4,0x3d353d35,0xbcc4bd6d,0xbd7bbc48,0x3d553d0e,0xbd0ebd55,0x3c483d7b,0x8000bd80,0xbcc43d6d,0x3d35bd35,0xbd6d3cc4,
0xbc483d7b,0x3d0ebd55,0xbd553d0e,0x3d7bbc48,0xbd800000,0x3d6d3cc4,0xbd35bd35,0x3cc43d6d,0x3d7b3c48,0xbd55bd0e,0x3d0e3d55,0xbc48bd7b,0x80003d80,0x3cc4bd6d,0xbd353d35,0x3d6dbcc4,
0x3d800000,0x3d800000,0x3d800000,0x3d800000,0x3d800000,0x3d800000,0x3d800000,0x3d800000,0x3d800000,0x3d800000,0x3d800000,0x3d800000,0x3d800000,0x3d800000,0x3d800000,0x3d800000,
0x3d800000,0x3d800000,0x3d800000,0x3d800000,0x3d800000,0x3d800000,0x3d800000,0x3d800000,0x3d800000,0x3d800000,0x3d800000,0x3d800000,0x3d800000,0x3d800000,0x3d800000,0x3d800000,
0x3d35bd35,0xbd35bd35,0xbd353d35,0x3d353d35,0x3d800000,0xbd80,0xbd800000,0x3d80,0x3d35bd35,0xbd35bd35,0xbd353d35,0x3d353d35,0x3d800000,0xbd80,0xbd800000,0x3d80,
0x3d35bd35,0xbd35bd35,0xbd353d35,0x3d353d35,0x3d800000,0xbd80,0xbd800000,0x3d80,0x3d35bd35,0xbd35bd35,0xbd353d35,0x3d353d35,0x3d800000,0xbd80,0xbd800000,0x3d80,
0xbd80,0xbcc4bd6d,0xbd35bd35,0xbd6dbcc4,0xbc48bd7b,0xbd0ebd55,0xbd55bd0e,0xbd7bbc48,0x3d800000,0x3d6dbcc4,0x3d35bd35,0x3cc4bd6d,0x3d7bbc48,0x3d55bd0e,0x3d0ebd55,0x3c48bd7b,
0x3d80,0x3cc43d6d,0x3d353d35,0x3d6d3cc4,0x3c483d7b,0x3d0e3d55,0x3d553d0e,0x3d7b3c48,0xbd800000,0xbd6d3cc4,0xbd353d35,0xbcc43d6d,0xbd7b3c48,0xbd553d0e,0xbd0e3d55,0xbc483d7b,
0xbd55bd0e,0xbc483d7b,0x3d7bbc48,0xbd0ebd55,0xbd80,0xbd6d3cc4,0x3d353d35,0x3cc4bd6d,0x3d0ebd55,0xbd7bbc48,0x3c483d7b,0x3d55bd0e,0x3d800000,0xbcc4bd6d,0xbd353d35,0x3d6d3cc4,
0x3d553d0e,0x3c48bd7b,0xbd7b3c48,0x3d0e3d55,0x3d80,0x3d6dbcc4,0xbd35bd35,0xbcc43d6d,0xbd0e3d55,0x3d7b3c48,0xbc48bd7b,0xbd553d0e,0xbd800000,0x3cc43d6d,0x3d35bd35,0xbd6dbcc4,
0x3d800000,0x3d35bd35,0xbd80,0xbd35bd35,0x3d6dbcc4,0x3cc4bd6d,0xbcc4bd6d,0xbd6dbcc4,0xbd800000,0xbd353d35,0x3d80,0x3d353d35,0xbd6d3cc4,0xbcc43d6d,0x3cc43d6d,0x3d6d3cc4,
0x3d800000,0x3d35bd35,0xbd80,0xbd35bd35,0x3d6dbcc4,0x3cc4bd6d,0xbcc4bd6d,0xbd6dbcc4,0xbd800000,0xbd353d35,0x3d80,0x3d353d35,0xbd6d3cc4,0xbcc43d6d,0x3cc43d6d,0x3d6d3cc4,
0x3cc4bd6d,0xbd6d3cc4,0x3d6d3cc4,0xbcc4bd6d,0x3d800000,0xbd35bd35,0x3d80,0x3d35bd35,0xbcc43d6d,0x3d6dbcc4,0xbd6dbcc4,0x3cc43d6d,0xbd800000,0x3d353d35,0xbd80,0xbd353d35,
0x3cc4bd6d,0xbd6d3cc4,0x3d6d3cc4,0xbcc4bd6d,0x3d800000,0xbd35bd35,0x3d80,0x3d35bd35,0xbcc43d6d,0x3d6dbcc4,0xbd6dbcc4,0x3cc43d6d,0xbd800000,0x3d353d35,0xbd80,0xbd353d35,
0xbd80,0xbd6dbcc4,0xbd353d35,0x3cc43d6d,0xbd0ebd55,0xbd7b3c48,0xbc483d7b,0x3d553d0e,0xbd800000,0xbcc43d6d,0x3d353d35,0x3d6dbcc4,0xbd553d0e,0x3c483d7b,0x3d7b3c48,0x3d0ebd55,
0x3d80,0x3d6d3cc4,0x3d35bd35,0xbcc4bd6d,0x3d0e3d55,0x3d7bbc48,0x3c48bd7b,0xbd55bd0e,0x3d800000,0x3cc4bd6d,0xbd35bd35,0xbd6d3cc4,0x3d55bd0e,0xbc48bd7b,0xbd7bbc48,0xbd0e3d55,
0xbd7bbc48,0x3d553d0e,0xbd0ebd55,0x3c483d7b,0xbd80,0xbcc43d6d,0x3d35bd35,0xbd6d3cc4,0xbc483d7b,0x3d0ebd55,0xbd553d0e,0x3d7bbc48,0xbd800000,0x3d6d3cc4,0xbd35bd35,0x3cc43d6d,
0x3d7b3c48,0xbd55bd0e,0x3d0e3d55,0xbc48bd7b,0x3d80,0x3cc4bd6d,0xbd353d35,0x3d6dbcc4,0x3c48bd7b,0xbd0e3d55,0x3d55bd0e,0xbd7b3c48,0x3d800000,0xbd6dbcc4,0x3d353d35,0xbcc4bd6d,
0x80003d80,0x8000bd80,0x80003d80,0x8000bd80,0x3d800000,0xbd800000,0x3d800000,0xbd800000,0x80003d80,0x8000bd80,0x80003d80,0x8000bd80,0x3d800000,0xbd800000,0x3d800000,0xbd800000,
0x80003d80,0x8000bd80,0x80003d80,0x8000bd80,0x3d800000,0xbd800000,0x3d800000,0xbd800000,0x80003d80,0x8000bd80,0x80003d80,0x8000bd80,0x3d800000,0xbd800000,0x3d800000,0xbd800000,
0x3d35bd35,0x3d353d35,0xbd353d35,0xbd35bd35,0x80003d80,0xbd800000,0x8000bd80,0x3d800000,0x3d35bd35,0x3d353d35,0xbd353d35,0xbd35bd35,0x80003d80,0xbd800000,0x8000bd80,0x3d800000,
0x3d35bd35,0x3d353d35,0xbd353d35,0xbd35bd35,0x80003d80,0xbd800000,0x8000bd80,0x3d800000,0x3d35bd35,0x3d353d35,0xbd353d35,0xbd35bd35,0x80003d80,0xbd800000,0x8000bd80,0x3d800000,
0x3d800000,0xbd6d3cc4,0x3d35bd35,0xbcc43d6d,0xbc48bd7b,0x3d0e3d55,0xbd55bd0e,0x3d7b3c48,0x80003d80,0xbcc4bd6d,0x3d353d35,0xbd6dbcc4,0x3d7bbc48,0xbd553d0e,0x3d0ebd55,0xbc483d7b,
0xbd800000,0x3d6dbcc4,0xbd353d35,0x3cc4bd6d,0x3c483d7b,0xbd0ebd55,0x3d553d0e,0xbd7bbc48,0x8000bd80,0x3cc43d6d,0xbd35bd35,0x3d6d3cc4,0xbd7b3c48,0x3d55bd0e,0xbd0e3d55,0x3c48bd7b,
0xbd55bd0e,0x3c48bd7b,0x3d7bbc48,0x3d0e3d55,0x3d800000,0x3cc43d6d,0xbd353d35,0xbd6dbcc4,0x3d0ebd55,0x3d7b3c48,0x3c483d7b,0xbd553d0e,0x80003d80,0xbd6d3cc4,0xbd35bd35,0x3cc4bd6d,
0x3d553d0e,0xbc483d7b,0xbd7b3c48,0xbd0ebd55,0xbd800000,0xbcc4bd6d,0x3d35bd35,0x3d6d3cc4,0xbd0e3d55,0xbd7bbc48,0xbc48bd7b,0x3d55bd0e,0x8000bd80,0x3d6dbcc4,0x3d353d35,0xbcc43d6d,
0x80003d80,0xbd35bd35,0x3d800000,0xbd353d35,0x3d6dbcc4,0xbcc43d6d,0xbcc4bd6d,0x3d6d3cc4,0x8000bd80,0x3d353d35,0xbd800000,0x3d35bd35,0xbd6d3cc4,0x3cc4bd6d,0x3cc43d6d,0xbd6dbcc4,
0x80003d80,0xbd35bd35,0x3d800000,0xbd353d35,0x3d6dbcc4,0xbcc43d6d,0xbcc4bd6d,0x3d6d3cc4,0x8000bd80,0x3d353d35,0xbd800000,0x3d35bd35,0xbd6d3cc4,0x3cc4bd6d,0x3cc43d6d,0xbd6dbcc4,
0x3cc4bd6d,0x3d6dbcc4,0x3d6d3cc4,0x3cc43d6d,0x80003d80,0xbd353d35,0xbd800000,0xbd35bd35,0xbcc43d6d,0xbd6d3cc4,0xbd6dbcc4,0xbcc4bd6d,0x8000bd80,0x3d35bd35,0x3d800000,0x3d353d35,
0x3cc4bd6d,0x3d6dbcc4,0x3d6d3cc4,0x3cc43d6d,0x80003d80,0xbd353d35,0xbd800000,0xbd35bd35,0xbcc43d6d,0xbd6d3cc4,0xbd6dbcc4,0xbcc4bd6d,0x8000bd80,0x3d35bd35,0x3d800000,0x3d353d35,
0x3d800000,0xbcc43d6d,0xbd35bd35,0x3d6dbcc4,0xbd0ebd55,0x3d7bbc48,0xbc483d7b,0xbd55bd0e,0x8000bd80,0x3d6d3cc4,0xbd353d35,0xbcc4bd6d,0xbd553d0e,0xbc48bd7b,0x3d7b3c48,0xbd0e3d55,
0xbd800000,0x3cc4bd6d,0x3d353d35,0xbd6d3cc4,0x3d0e3d55,0xbd7b3c48,0x3c48bd7b,0x3d553d0e,0x80003d80,0xbd6dbcc4,0x3d35bd35,0x3cc43d6d,0x3d55bd0e,0x3c483d7b,0xbd7bbc48,0x3d0ebd55,
0xbd7bbc48,0xbd55bd0e,0xbd0ebd55,0xbc48bd7b,0x3d800000,0x3d6d3cc4,0x3d353d35,0x3cc43d6d,0xbc483d7b,0xbd0e3d55,0xbd553d0e,0xbd7b3c48,0x8000bd80,0x3cc4bd6d,0x3d35bd35,0x3d6dbcc4,
0x3d7b3c48,0x3d553d0e,0x3d0e3d55,0x3c483d7b,0xbd800000,0xbd6dbcc4,0xbd35bd35,0xbcc4bd6d,0x3c48bd7b,0x3d0ebd55,0x3d55bd0e,0x3d7bbc48,0x80003d80,0xbcc43d6d,0xbd353d35,0xbd6d3cc4,
0x3d800000,0xbd800000,0x3d800000,0xbd800000,0xbd80,0x3d80,0xbd80,0x3d80,0x3d800000,0xbd800000,0x3d800000,0xbd800000,0xbd80,0x3d80,0xbd80,0x3d80,
0x3d800000,0xbd800000,0x3d800000,0xbd800000,0xbd80,0x3d80,0xbd80,0x3d80,0x3d800000,0xbd800000,0x3d800000,0xbd800000,0xbd80,0x3d80,0xbd80,0x3d80,
0xbd35bd35,0x3d35bd35,0x3d353d35,0xbd353d35,0x3d800000,0x3d80,0xbd800000,0xbd80,0xbd35bd35,0x3d35bd35,0x3d353d35,0xbd353d35,0x3d800000,0x3d80,0xbd800000,0xbd80,
0xbd35bd35,0x3d35bd35,0x3d353d35,0xbd353d35,0x3d800000,0x3d80,0xbd800000,0xbd80,0xbd35bd35,0x3d35bd35,0x3d353d35,0xbd353d35,0x3d800000,0x3d80,0xbd800000,0xbd80,
0xbd80,0x3cc43d6d,0xbd35bd35,0x3d6d3cc4,0xbd7b3c48,0x3d55bd0e,0xbd0e3d55,0x3c48bd7b,0x3d800000,0xbd6d3cc4,0x3d35bd35,0xbcc43d6d,0xbc48bd7b,0x3d0e3d55,0xbd55bd0e,0x3d7b3c48,
0x3d80,0xbcc4bd6d,0x3d353d35,0xbd6dbcc4,0x3d7bbc48,0xbd553d0e,0x3d0ebd55,0xbc483d7b,0xbd800000,0x3d6dbcc4,0xbd353d35,0x3cc4bd6d,0x3c483d7b,0xbd0ebd55,0x3d553d0e,0xbd7bbc48,
0xbd0e3d55,0xbd7bbc48,0xbc48bd7b,0x3d55bd0e,0xbd80,0x3d6dbcc4,0x3d353d35,0xbcc43d6d,0xbd55bd0e,0x3c48bd7b,0x3d7bbc48,0x3d0e3d55,0x3d800000,0x3cc43d6d,0xbd353d35,0xbd6dbcc4,
0x3d0ebd55,0x3d7b3c48,0x3c483d7b,0xbd553d0e,0x3d80,0xbd6d3cc4,0xbd35bd35,0x3cc4bd6d,0x3d553d0e,0xbc483d7b,0xbd7b3c48,0xbd0ebd55,0xbd800000,0xbcc4bd6d,0x3d35bd35,0x3d6d3cc4,
0x3d800000,0xbd353d35,0xbd80,0x3d353d35,0xbcc4bd6d,0x3d6d3cc4,0xbd6d3cc4,0x3cc4bd6d,0xbd800000,0x3d35bd35,0x3d80,0xbd35bd35,0x3cc43d6d,0xbd6dbcc4,0x3d6dbcc4,0xbcc43d6d,
0x3d800000,0xbd353d35,0xbd80,0x3d353d35,0xbcc4bd6d,0x3d6d3cc4,0xbd6d3cc4,0x3cc4bd6d,0xbd800000,0x3d35bd35,0x3d80,0xbd35bd35,0x3cc43d6d,0xbd6dbcc4,0x3d6dbcc4,0xbcc43d6d,
0xbd6dbcc4,0xbcc4bd6d,0x3cc4bd6d,0x3d6dbcc4,0x3d800000,0x3d353d35,0x3d80,0xbd353d35,0x3d6d3cc4,0x3cc43d6d,0xbcc43d6d,0xbd6d3cc4,0xbd800000,0xbd35bd35,0xbd80,0x3d35bd35,
0xbd6dbcc4,0xbcc4bd6d,0x3cc4bd6d,0x3d6dbcc4,0x3d800000,0x3d353d35,0x3d80,0xbd353d35,0x3d6d3cc4,0x3cc43d6d,0xbcc43d6d,0xbd6d3cc4,0xbd800000,0xbd35bd35,0xbd80,0x3d35bd35,
0xbd80,0x3d6d3cc4,0xbd353d35,0xbcc4bd6d,0xbd553d0e,0xbc48bd7b,0x3d7b3c48,0xbd0e3d55,0xbd800000,0x3cc4bd6d,0x3d353d35,0xbd6d3cc4,0x3d0e3d55,0xbd7b3c48,0x3c48bd7b,0x3d553d0e,
0x3d80,0xbd6dbcc4,0x3d35bd35,0x3cc43d6d,0x3d55bd0e,0x3c483d7b,0xbd7bbc48,0x3d0ebd55,0x3d800000,0xbcc43d6d,0xbd35bd35,0x3d6dbcc4,0xbd0ebd55,0x3d7bbc48,0xbc483d7b,0xbd55bd0e,
0xbc483d7b,0xbd0e3d55,0xbd553d0e,0xbd7b3c48,0xbd80,0x3cc4bd6d,0x3d35bd35,0x3d6dbcc4,0x3d7b3c48,0x3d553d0e,0x3d0e3d55,0x3c483d7b,0xbd800000,0xbd6dbcc4,0xbd35bd35,0xbcc4bd6d,
0x3c48bd7b,0x3d0ebd55,0x3d55bd0e,0x3d7bbc48,0x3d80,0xbcc43d6d,0xbd353d35,0xbd6d3cc4,0xbd7bbc48,0xbd55bd0e,0xbd0ebd55,0xbc48bd7b,0x3d800000,0x3d6d3cc4,0x3d353d35,0x3cc43d6d,
0x80003d80,0x80003d80,0x80003d80,0x80003d80,0x8000bd80,0x8000bd80,0x8000bd80,0x8000bd80,0x80003d80,0x80003d80,0x80003d80,0x80003d80,0x8000bd80,0x8000bd80,0x8000bd80,0x8000bd80,
0x80003d80,0x80003d80,0x80003d80,0x80003d80,0x8000bd80,0x8000bd80,0x8000bd80,0x8000bd80,0x80003d80,0x80003d80,0x80003d80,0x80003d80,0x8000bd80,0x8000bd80,0x8000bd80,0x8000bd80,
0xbd35bd35,0xbd353d35,0x3d353d35,0x3d35bd35,0x80003d80,0x3d800000,0x8000bd80,0xbd800000,0xbd35bd35,0xbd353d35,0x3d353d35,0x3d35bd35,0x80003d80,0x3d800000,0x8000bd80,0xbd800000,
0xbd35bd35,0xbd353d35,0x3d353d35,0x3d35bd35,0x80003d80,0x3d800000,0x8000bd80,0xbd800000,0xbd35bd35,0xbd353d35,0x3d353d35,0x3d35bd35,0x80003d80,0x3d800000,0x8000bd80,0xbd800000,
0x3d800000,0x3d6dbcc4,0x3d35bd35,0x3cc4bd6d,0xbd7b3c48,0xbd553d0e,0xbd0e3d55,0xbc483d7b,0x80003d80,0x3cc43d6d,0x3d353d35,0x3d6d3cc4,0xbc48bd7b,0xbd0ebd55,0xbd55bd0e,0xbd7bbc48,
0xbd800000,0xbd6d3cc4,0xbd353d35,0xbcc43d6d,0x3d7bbc48,0x3d55bd0e,0x3d0ebd55,0x3c48bd7b,0x8000bd80,0xbcc4bd6d,0xbd35bd35,0xbd6dbcc4,0x3c483d7b,0x3d0e3d55,0x3d553d0e,0x3d7b3c48,
0xbd0e3d55,0x3d7b3c48,0xbc48bd7b,0xbd553d0e,0x3d800000,0xbcc4bd6d,0xbd353d35,0x3d6d3cc4,0xbd55bd0e,0xbc483d7b,0x3d7bbc48,0xbd0ebd55,0x80003d80,0x3d6dbcc4,0xbd35bd35,0xbcc43d6d,
0x3d0ebd55,0xbd7bbc48,0x3c483d7b,0x3d55bd0e,0xbd800000,0x3cc43d6d,0x3d35bd35,0xbd6dbcc4,0x3d553d0e,0x3c48bd7b,0xbd7b3c48,0x3d0e3d55,0x8000bd80,0xbd6d3cc4,0x3d353d35,0x3cc4bd6d,
0x80003d80,0x3d353d35,0x3d800000,0x3d35bd35,0xbcc4bd6d,0xbd6dbcc4,0xbd6d3cc4,0xbcc43d6d,0x8000bd80,0xbd35bd35,0xbd800000,0xbd353d35,0x3cc43d6d,0x3d6d3cc4,0x3d6dbcc4,0x3cc4bd6d,
0x80003d80,0x3d353d35,0x3d800000,0x3d35bd35,0xbcc4bd6d,0xbd6dbcc4,0xbd6d3cc4,0xbcc43d6d,0x8000bd80,0xbd35bd35,0xbd800000,0xbd353d35,0x3cc43d6d,0x3d6d3cc4,0x3d6dbcc4,0x3cc4bd6d,
0xbd6dbcc4,0x3cc43d6d,0x3cc4bd6d,0xbd6d3cc4,0x80003d80,0x3d35bd35,0xbd800000,0x3d353d35,0x3d6d3cc4,0xbcc4bd6d,0xbcc43d6d,0x3d6dbcc4,0x8000bd80,0xbd353d35,0x3d800000,0xbd35bd35,
0xbd6dbcc4,0x3cc43d6d,0x3cc4bd6d,0xbd6d3cc4,0x80003d80,0x3d35bd35,0xbd800000,0x3d353d35,0x3d6d3cc4,0xbcc4bd6d,0xbcc43d6d,0x3d6dbcc4,0x8000bd80,0xbd353d35,0x3d800000,0xbd35bd35,
0x3d800000,0x3cc4bd6d,0xbd35bd35,0xbd6d3cc4,0xbd553d0e,0x3c483d7b,0x3d7b3c48,0x3d0ebd55,0x8000bd80,0xbd6dbcc4,0xbd353d35,0x3cc43d6d,0x3d0e3d55,0x3d7bbc48,0x3c48bd7b,0xbd55bd0e,
0xbd800000,0xbcc43d6d,0x3d353d35,0x3d6dbcc4,0x3d55bd0e,0xbc48bd7b,0xbd7bbc48,0xbd0e3d55,0x80003d80,0x3d6d3cc4,0x3d35bd35,0xbcc4bd6d,0xbd0ebd55,0xbd7b3c48,0xbc483d7b,0x3d553d0e,
0xbc483d7b,0x3d0ebd55,0xbd553d0e,0x3d7bbc48,0x3d800000,0xbd6dbcc4,0x3d353d35,0xbcc4bd6d,0x3d7b3c48,0xbd55bd0e,0x3d0e3d55,0xbc48bd7b,0x8000bd80,0xbcc43d6d,0x3d35bd35,0xbd6d3cc4,
0x3c48bd7b,0xbd0e3d55,0x3d55bd0e,0xbd7b3c48,0xbd800000,0x3d6d3cc4,0xbd35bd35,0x3cc43d6d,0xbd7bbc48,0x3d553d0e,0xbd0ebd55,0x3c483d7b,0x80003d80,0x3cc4bd6d,0xbd353d35,0x3d6dbcc4,
0x3d800000,0x3d800000,0x3d800000,0x3d800000,0xbd800000,0xbd800000,0xbd800000,0xbd800000,0x3d800000,0x3d800000,0x3d800000,0x3d800000,0xbd800000,0xbd800000,0xbd800000,0xbd800000,
0x3d800000,0x3d800000,0x3d800000,0x3d800000,0xbd800000,0xbd800000,0xbd800000,0xbd800000,0x3d800000,0x3d800000,0x3d800000,0x3d800000,0xbd800000,0xbd800000,0xbd800000,0xbd800000,
0xbd353d35,0x3d353d35,0x3d35bd35,0xbd35bd35,0x3d800000,0xbd80,0xbd800000,0x3d80,0xbd353d35,0x3d353d35,0x3d35bd35,0xbd35bd35,0x3d800000,0xbd80,0xbd800000,0x3d80,
0xbd353d35,0x3d353d35,0x3d35bd35,0xbd35bd35,0x3d800000,0xbd80,0xbd800000,0x3d80,0xbd353d35,0x3d353d35,0x3d35bd35,0xbd35bd35,0x3d800000,0xbd80,0xbd800000,0x3d80,
0xbd80,0xbcc4bd6d,0xbd35bd35,0xbd6dbcc4,0x3c483d7b,0x3d0e3d55,0x3d553d0e,0x3d7b3c48,0x3d800000,0x3d6dbcc4,0x3d35bd35,0x3cc4bd6d,0xbd7b3c48,0xbd553d0e,0xbd0e3d55,0xbc483d7b,
0x3d80,0x3cc43d6d,0x3d353d35,0x3d6d3cc4,0xbc48bd7b,0xbd0ebd55,0xbd55bd0e,0xbd7bbc48,0xbd800000,0xbd6d3cc4,0xbd353d35,0xbcc43d6d,0x3d7bbc48,0x3d55bd0e,0x3d0ebd55,0x3c48bd7b,
0x3d553d0e,0x3c48bd7b,0xbd7b3c48,0x3d0e3d55,0xbd80,0xbd6d3cc4,0x3d353d35,0x3cc4bd6d,0xbd0e3d55,0x3d7b3c48,0xbc48bd7b,0xbd553d0e,0x3d800000,0xbcc4bd6d,0xbd353d35,0x3d6d3cc4,
0xbd55bd0e,0xbc483d7b,0x3d7bbc48,0xbd0ebd55,0x3d80,0x3d6dbcc4,0xbd35bd35,0xbcc43d6d,0x3d0ebd55,0xbd7bbc48,0x3c483d7b,0x3d55bd0e,0xbd800000,0x3cc43d6d,0x3d35bd35,0xbd6dbcc4,
0x3d800000,0x3d35bd35,0xbd80,0xbd35bd35,0xbd6d3cc4,0xbcc43d6d,0x3cc43d6d,0x3d6d3cc4,0xbd800000,0xbd353d35,0x3d80,0x3d353d35,0x3d6dbcc4,0x3cc4bd6d,0xbcc4bd6d,0xbd6dbcc4,
0x3d800000,0x3d35bd35,0xbd80,0xbd35bd35,0xbd6d3cc4,0xbcc43d6d,0x3cc43d6d,0x3d6d3cc4,0xbd800000,0xbd353d35,0x3d80,0x3d353d35,0x3d6dbcc4,0x3cc4bd6d,0xbcc4bd6d,0xbd6dbcc4,
0xbcc43d6d,0x3d6dbcc4,0xbd6dbcc4,0x3cc43d6d,0x3d800000,0xbd35bd35,0x3d80,0x3d35bd35,0x3cc4bd6d,0xbd6d3cc4,0x3d6d3cc4,0xbcc4bd6d,0xbd800000,0x3d353d35,0xbd80,0xbd353d35,
0xbcc43d6d,0x3d6dbcc4,0xbd6dbcc4,0x3cc43d6d,0x3d800000,0xbd35bd35,0x3d80,0x3d35bd35,0x3cc4bd6d,0xbd6d3cc4,0x3d6d3cc4,0xbcc4bd6d,0xbd800000,0x3d353d35,0xbd80,0xbd353d35,
0xbd80,0xbd6dbcc4,0xbd353d35,0x3cc43d6d,0x3d0e3d55,0x3d7bbc48,0x3c48bd7b,0xbd55bd0e,0xbd800000,0xbcc43d6d,0x3d353d35,0x3d6dbcc4,0x3d55bd0e,0xbc48bd7b,0xbd7bbc48,0xbd0e3d55,
0x3d80,0x3d6d3cc4,0x3d35bd35,0xbcc4bd6d,0xbd0ebd55,0xbd7b3c48,0xbc483d7b,0x3d553d0e,0x3d800000,0x3cc4bd6d,0xbd35bd35,0xbd6d3cc4,0xbd553d0e,0x3c483d7b,0x3d7b3c48,0x3d0ebd55,
0x3d7b3c48,0xbd55bd0e,0x3d0e3d55,0xbc48bd7b,0xbd80,0xbcc43d6d,0x3d35bd35,0xbd6d3cc4,0x3c48bd7b,0xbd0e3d55,0x3d55bd0e,0xbd7b3c48,0xbd800000,0x3d6d3cc4,0xbd35bd35,0x3cc43d6d,
0xbd7bbc48,0x3d553d0e,0xbd0ebd55,0x3c483d7b,0x3d80,0x3cc4bd6d,0xbd353d35,0x3d6dbcc4,0xbc483d7b,0x3d0ebd55,0xbd553d0e,0x3d7bbc48,0x3d800000,0xbd6dbcc4,0x3d353d35,0xbcc4bd6d,
0x80003d80,0x8000bd80,0x80003d80,0x8000bd80,0xbd800000,0x3d800000,0xbd800000,0x3d800000,0x80003d80,0x8000bd80,0x80003d80,0x8000bd80,0xbd800000,0x3d800000,0xbd800000,0x3d800000,
0x80003d80,0x8000bd80,0x80003d80,0x8000bd80,0xbd800000,0x3d800000,0xbd800000,0x3d800000,0x80003d80,0x8000bd80,0x80003d80,0x8000bd80,0xbd800000,0x3d800000,0xbd800000,0x3d800000,
0xbd353d35,0xbd35bd35,0x3d35bd35,0x3d353d35,0x80003d80,0xbd800000,0x8000bd80,0x3d800000,0xbd353d35,0xbd35bd35,0x3d35bd35,0x3d353d35,0x80003d80,0xbd800000,0x8000bd80,0x3d800000,
0xbd353d35,0xbd35bd35,0x3d35bd35,0x3d353d35,0x80003d80,0xbd800000,0x8000bd80,0x3d800000,0xbd353d35,0xbd35bd35,0x3d35bd35,0x3d353d35,0x80003d80,0xbd800000,0x8000bd80,0x3d800000,
0x3d800000,0xbd6d3cc4,0x3d35bd35,0xbcc43d6d,0x3c483d7b,0xbd0ebd55,0x3d553d0e,0xbd7bbc48,0x80003d80,0xbcc4bd6d,0x3d353d35,0xbd6dbcc4,0xbd7b3c48,0x3d55bd0e,0xbd0e3d55,0x3c48bd7b,
0xbd800000,0x3d6dbcc4,0xbd353d35,0x3cc4bd6d,0xbc48bd7b,0x3d0e3d55,0xbd55bd0e,0x3d7b3c48,0x8000bd80,0x3cc43d6d,0xbd35bd35,0x3d6d3cc4,0x3d7bbc48,0xbd553d0e,0x3d0ebd55,0xbc483d7b,
0x3d553d0e,0xbc483d7b,0xbd7b3c48,0xbd0ebd55,0x3d800000,0x3cc43d6d,0xbd353d35,0xbd6dbcc4,0xbd0e3d55,0xbd7bbc48,0xbc48bd7b,0x3d55bd0e,0x80003d80,0xbd6d3cc4,0xbd35bd35,0x3cc4bd6d,
0xbd55bd0e,0x3c48bd7b,0x3d7bbc48,0x3d0e3d55,0xbd800000,0xbcc4bd6d,0x3d35bd35,0x3d6d3cc4,0x3d0ebd55,0x3d7b3c48,0x3c483d7b,0xbd553d0e,0x8000bd80,0x3d6dbcc4,0x3d353d35,0xbcc43d6d,
0x80003d80,0xbd35bd35,0x3d800000,0xbd353d35,0xbd6d3cc4,0x3cc4bd6d,0x3cc43d6d,0xbd6dbcc4,0x8000bd80,0x3d353d35,0xbd800000,0x3d35bd35,0x3d6dbcc4,0xbcc43d6d,0xbcc4bd6d,0x3d6d3cc4,
0x80003d80,0xbd35bd35,0x3d800000,0xbd353d35,0xbd6d3cc4,0x3cc4bd6d,0x3cc43d6d,0xbd6dbcc4,0x8000bd80,0x3d353d35,0xbd800000,0x3d35bd35,0x3d6dbcc4,0xbcc43d6d,0xbcc4bd6d,0x3d6d3cc4,
0xbcc43d6d,0xbd6d3cc4,0xbd6dbcc4,0xbcc4bd6d,0x80003d80,0xbd353d35,0xbd800000,0xbd35bd35,0x3cc4bd6d,0x3d6dbcc4,0x3d6d3cc4,0x3cc43d6d,0x8000bd80,0x3d35bd35,0x3d800000,0x3d353d35,
0xbcc43d6d,0xbd6d3cc4,0xbd6dbcc4,0xbcc4bd6d,0x80003d80,0xbd353d35,0xbd800000,0xbd35bd35,0x3cc4bd6d,0x3d6dbcc4,0x3d6d3cc4,0x3cc43d6d,0x8000bd80,0x3d35bd35,0x3d800000,0x3d353d35,
0x3d800000,0xbcc43d6d,0xbd35bd35,0x3d6dbcc4,0x3d0e3d55,0xbd7b3c48,0x3c48bd7b,0x3d553d0e,0x8000bd80,0x3d6d3cc4,0xbd353d35,0xbcc4bd6d,0x3d55bd0e,0x3c483d7b,0xbd7bbc48,0x3d0ebd55,
0xbd800000,0x3cc4bd6d,0x3d353d35,0xbd6d3cc4,0xbd0ebd55,0x3d7bbc48,0xbc483d7b,0xbd55bd0e,0x80003d80,0xbd6dbcc4,0x3d35bd35,0x3cc43d6d,0xbd553d0e,0xbc48bd7b,0x3d7b3c48,0xbd0e3d55,
0x3d7b3c48,0x3d553d0e,0x3d0e3d55,0x3c483d7b,0x3d800000,0x3d6d3cc4,0x3d353d35,0x3cc43d6d,0x3c48bd7b,0x3d0ebd55,0x3d55bd0e,0x3d7bbc48,0x8000bd80,0x3cc4bd6d,0x3d35bd35,0x3d6dbcc4,
0xbd7bbc48,0xbd55bd0e,0xbd0ebd55,0xbc48bd7b,0xbd800000,0xbd6dbcc4,0xbd35bd35,0xbcc4bd6d,0xbc483d7b,0xbd0e3d55,0xbd553d0e,0xbd7b3c48,0x80003d80,0xbcc43d6d,0xbd353d35,0xbd6d3cc4,
0x3d800000,0xbd800000,0x3d800000,0xbd800000,0x3d80,0xbd80,0x3d80,0xbd80,0x3d800000,0xbd800000,0x3d800000,0xbd800000,0x3d80,0xbd80,0x3d80,0xbd80,
0x3d800000,0xbd800000,0x3d800000,0xbd800000,0x3d80,0xbd80,0x3d80,0xbd80,0x3d800000,0xbd800000,0x3d800000,0xbd800000,0x3d80,0xbd80,0x3d80,0xbd80,
0x3d353d35,0xbd353d35,0xbd35bd35,0x3d35bd35,0x3d800000,0x3d80,0xbd800000,0xbd80,0x3d353d35,0xbd353d35,0xbd35bd35,0x3d35bd35,0x3d800000,0x3d80,0xbd800000,0xbd80,
0x3d353d35,0xbd353d35,0xbd35bd35,0x3d35bd35,0x3d800000,0x3d80,0xbd800000,0xbd80,0x3d353d35,0xbd353d35,0xbd35bd35,0x3d35bd35,0x3d800000,0x3d80,0xbd800000,0xbd80,
0xbd80,0x3cc43d6d,0xbd35bd35,0x3d6d3cc4,0x3d7bbc48,0xbd553d0e,0x3d0ebd55,0xbc483d7b,0x3d800000,0xbd6d3cc4,0x3d35bd35,0xbcc43d6d,0x3c483d7b,0xbd0ebd55,0x3d553d0e,0xbd7bbc48,
0x3d80,0xbcc4bd6d,0x3d353d35,0xbd6dbcc4,0xbd7b3c48,0x3d55bd0e,0xbd0e3d55,0x3c48bd7b,0xbd800000,0x3d6dbcc4,0xbd353d35,0x3cc4bd6d,0xbc48bd7b,0x3d0e3d55,0xbd55bd0e,0x3d7b3c48,
0x3d0ebd55,0x3d7b3c48,0x3c483d7b,0xbd553d0e,0xbd80,0x3d6dbcc4,0x3d353d35,0xbcc43d6d,0x3d553d0e,0xbc483d7b,0xbd7b3c48,0xbd0ebd55,0x3d800000,0x3cc43d6d,0xbd353d35,0xbd6dbcc4,
0xbd0e3d55,0xbd7bbc48,0xbc48bd7b,0x3d55bd0e,0x3d80,0xbd6d3cc4,0xbd35bd35,0x3cc4bd6d,0xbd55bd0e,0x3c48bd7b,0x3d7bbc48,0x3d0e3d55,0xbd800000,0xbcc4bd6d,0x3d35bd35,0x3d6d3cc4,
0x3d800000,0xbd353d35,0xbd80,0x3d353d35,0x3cc43d6d,0xbd6dbcc4,0x3d6dbcc4,0xbcc43d6d,0xbd800000,0x3d35bd35,0x3d80,0xbd35bd35,0xbcc4bd6d,0x3d6d3cc4,0xbd6d3cc4,0x3cc4bd6d,
0x3d800000,0xbd353d35,0xbd80,0x3d353d35,0x3cc43d6d,0xbd6dbcc4,0x3d6dbcc4,0xbcc43d6d,0xbd800000,0x3d35bd35,0x3d80,0xbd35bd35,0xbcc4bd6d,0x3d6d3cc4,0xbd6d3cc4,0x3cc4bd6d,
0x3d6d3cc4,0x3cc43d6d,0xbcc43d6d,0xbd6d3cc4,0x3d800000,0x3d353d35,0x3d80,0xbd353d35,0xbd6dbcc4,0xbcc4bd6d,0x3cc4bd6d,0x3d6dbcc4,0xbd800000,0xbd35bd35,0xbd80,0x3d35bd35,
0x3d6d3cc4,0x3cc43d6d,0xbcc43d6d,0xbd6d3cc4,0x3d800000,0x3d353d35,0x3d80,0xbd353d35,0xbd6dbcc4,0xbcc4bd6d,0x3cc4bd6d,0x3d6dbcc4,0xbd800000,0xbd35bd35,0xbd80,0x3d35bd35,
0xbd80,0x3d6d3cc4,0xbd353d35,0xbcc4bd6d,0x3d55bd0e,0x3c483d7b,0xbd7bbc48,0x3d0ebd55,0xbd800000,0x3cc4bd6d,0x3d353d35,0xbd6d3cc4,0xbd0ebd55,0x3d7bbc48,0xbc483d7b,0xbd55bd0e,
0x3d80,0xbd6dbcc4,0x3d35bd35,0x3cc43d6d,0xbd553d0e,0xbc48bd7b,0x3d7b3c48,0xbd0e3d55,0x3d800000,0xbcc43d6d,0xbd35bd35,0x3d6dbcc4,0x3d0e3d55,0xbd7b3c48,0x3c48bd7b,0x3d553d0e,
0x3c48bd7b,0x3d0ebd55,0x3d55bd0e,0x3d7bbc48,0xbd80,0x3cc4bd6d,0x3d35bd35,0x3d6dbcc4,0xbd7bbc48,0xbd55bd0e,0xbd0ebd55,0xbc48bd7b,0xbd800000,0xbd6dbcc4,0xbd35bd35,0xbcc4bd6d,
0xbc483d7b,0xbd0e3d55,0xbd553d0e,0xbd7b3c48,0x3d80,0xbcc43d6d,0xbd353d35,0xbd6d3cc4,0x3d7b3c48,0x3d553d0e,0x3d0e3d55,0x3c483d7b,0x3d800000,0x3d6d3cc4,0x3d353d35,0x3cc43d6d,
0x3d80,0x3d80,0x3d80,0x3d80,0x3d80,0x3d80,0x3d80,0x3d80,0x3d80,0x3d80,0x3d80,0x3d80,0x3d80,0x3d80,0x3d80,0x3d80,
0x3d80,0x3d80,0x3d80,0x3d80,0x3d80,0x3d80,0x3d80,0x3d80,0x3d80,0x3d80,0x3d80,0x3d80,0x3d80,0x3d80,0x3d80,0x3d80,
0xbd353d35,0xbd553d0e,0xbd6d3cc4,0xbd7b3c48,0x3d80,0xbc483d7b,0xbcc43d6d,0xbd0e3d55,0xbd35bd35,0xbd0ebd55,0xbcc4bd6d,0xbc48bd7b,0xbd800000,0xbd7bbc48,0xbd6dbcc4,0xbd55bd0e,
0x3d35bd35,0x3d55bd0e,0x3d6dbcc4,0x3d7bbc48,0xbd80,0x3c48bd7b,0x3cc4bd6d,0x3d0ebd55,0x3d353d35,0x3d0e3d55,0x3cc43d6d,0x3c483d7b,0x3d800000,0x3d7b3c48,0x3d6d3cc4,0x3d553d0e,
0xbd80,0x3cc4bd6d,0x3d35bd35,0x3d6dbcc4,0x3d800000,0x3d6d3cc4,0x3d353d35,0x3cc43d6d,0x3d80,0xbcc43d6d,0xbd353d35,0xbd6d3cc4,0xbd800000,0xbd6dbcc4,0xbd35bd35,0xbcc4bd6d,
0xbd80,0x3cc4bd6d,0x3d35bd35,0x3d6dbcc4,0x3d800000,0x3d6d3cc4,0x3d353d35,0x3cc43d6d,0x3d80,0xbcc43d6d,0xbd353d35,0xbd6d3cc4,0xbd800000,0xbd6dbcc4,0xbd35bd35,0xbcc4bd6d,
0xbd353d35,0xbd7b3c48,0xbd6dbcc4,0xbd0ebd55,0x3d800000,0x3d553d0e,0x3cc43d6d,0xbc483d7b,0xbd35bd35,0xbc48bd7b,0x3cc4bd6d,0x3d55bd0e,0x3d80,0xbd0e3d55,0xbd6d3cc4,0xbd7bbc48,
0x3d35bd35,0x3d7bbc48,0x3d6d3cc4,0x3d0e3d55,0xbd800000,0xbd55bd0e,0xbcc4bd6d,0x3c48bd7b,0x3d353d35,0x3c483d7b,0xbcc43d6d,0xbd553d0e,0xbd80,0x3d0ebd55,0x3d6dbcc4,0x3d7b3c48,
0x3d80,0xbd353d35,0xbd800000,0xbd35bd35,0xbd80,0x3d35bd35,0x3d800000,0x3d353d35,0x3d80,0xbd353d35,0xbd800000,0xbd35bd35,0xbd80,0x3d35bd35,0x3d800000,0x3d353d35,
0x3d80,0xbd353d35,0xbd800000,0xbd35bd35,0xbd80,0x3d35bd35,0x3d800000,0x3d353d35,0x3d80,0xbd353d35,0xbd800000,0xbd35bd35,0xbd80,0x3d35bd35,0x3d800000,0x3d353d35,
0xbd353d35,0xbd7bbc48,0xbcc4bd6d,0x3d0ebd55,0xbd80,0x3d55bd0e,0x3d6d3cc4,0x3c483d7b,0xbd35bd35,0x3c48bd7b,0x3d6dbcc4,0x3d553d0e,0x3d800000,0x3d0e3d55,0xbcc43d6d,0xbd7b3c48,
0x3d35bd35,0x3d7b3c48,0x3cc43d6d,0xbd0e3d55,0x3d80,0xbd553d0e,0xbd6dbcc4,0xbc48bd7b,0x3d353d35,0xbc483d7b,0xbd6d3cc4,0xbd55bd0e,0xbd800000,0xbd0ebd55,0x3cc4bd6d,0x3d7bbc48,
0xbd80,0x3d6dbcc4,0x3d353d35,0xbcc43d6d,0xbd800000,0xbcc4bd6d,0x3d35bd35,0x3d6d3cc4,0x3d80,0xbd6d3cc4,0xbd35bd35,0x3cc4bd6d,0x3d800000,0x3cc43d6d,0xbd353d35,0xbd6dbcc4,
0xbd80,0x3d6dbcc4,0x3d353d35,0xbcc43d6d,0xbd800000,0xbcc4bd6d,0x3d35bd35,0x3d6d3cc4,0x3d80,0xbd6d3cc4,0xbd35bd35,0x3cc4bd6d,0x3d800000,0x3cc43d6d,0xbd353d35,0xbd6dbcc4,
0xbd353d35,0xbd55bd0e,0x3cc4bd6d,0x3d7b3c48,0xbd800000,0xbc48bd7b,0x3d6dbcc4,0x3d0e3d55,0xbd35bd35,0x3d0ebd55,0x3d6d3cc4,0xbc483d7b,0xbd80,0x3d7bbc48,0x3cc43d6d,0xbd553d0e,
0x3d35bd35,0x3d553d0e,0xbcc43d6d,0xbd7bbc48,0x3d800000,0x3c483d7b,0xbd6d3cc4,0xbd0ebd55,0x3d353d35,0xbd0e3d55,0xbd6dbcc4,0x3c48bd7b,0x3d80,0xbd7b3c48,0xbcc4bd6d,0x3d55bd0e,
0xbd800000,0xbd800000,0xbd800000,0xbd800000,0xbd800000,0xbd800000,0xbd800000,0xbd800000,0xbd800000,0xbd800000,0xbd800000,0xbd800000,0xbd800000,0xbd800000,0xbd800000,0xbd800000,
0xbd800000,0xbd800000,0xbd800000,0xbd800000,0xbd800000,0xbd800000,0xbd800000,0xbd800000,0xbd800000,0xbd800000,0xbd800000,0xbd800000,0xbd800000,0xbd800000,0xbd800000,0xbd800000,
0xbd35bd35,0xbd0ebd55,0xbcc4bd6d,0xbc48bd7b,0xbd800000,0xbd7bbc48,0xbd6dbcc4,0xbd55bd0e,0x3d35bd35,0x3d55bd0e,0x3d6dbcc4,0x3d7bbc48,0x8000bd80,0x3c48bd7b,0x3cc4bd6d,0x3d0ebd55,
0x3d353d35,0x3d0e3d55,0x3cc43d6d,0x3c483d7b,0x3d800000,0x3d7b3c48,0x3d6d3cc4,0x3d553d0e,0xbd353d35,0xbd553d0e,0xbd6d3cc4,0xbd7b3c48,0x80003d80,0xbc483d7b,0xbcc43d6d,0xbd0e3d55,
0x3d800000,0x3d6d3cc4,0x3d353d35,0x3cc43d6d,0x80003d80,0xbcc43d6d,0xbd353d35,0xbd6d3cc4,0xbd800000,0xbd6dbcc4,0xbd35bd35,0xbcc4bd6d,0x8000bd80,0x3cc4bd6d,0x3d35bd35,0x3d6dbcc4,
0x3d800000,0x3d6d3cc4,0x3d353d35,0x3cc43d6d,0x80003d80,0xbcc43d6d,0xbd353d35,0xbd6d3cc4,0xbd800000,0xbd6dbcc4,0xbd35bd35,0xbcc4bd6d,0x8000bd80,0x3cc4bd6d,0x3d35bd35,0x3d6dbcc4,
0xbd35bd35,0xbc48bd7b,0x3cc4bd6d,0x3d55bd0e,0x80003d80,0xbd0e3d55,0xbd6d3cc4,0xbd7bbc48,0x3d35bd35,0x3d7bbc48,0x3d6d3cc4,0x3d0e3d55,0xbd800000,0xbd55bd0e,0xbcc4bd6d,0x3c48bd7b,
0x3d353d35,0x3c483d7b,0xbcc43d6d,0xbd553d0e,0x8000bd80,0x3d0ebd55,0x3d6dbcc4,0x3d7b3c48,0xbd353d35,0xbd7b3c48,0xbd6dbcc4,0xbd0ebd55,0x3d800000,0x3d553d0e,0x3cc43d6d,0xbc483d7b,
0xbd800000,0xbd35bd35,0x8000bd80,0x3d35bd35,0x3d800000,0x3d353d35,0x80003d80,0xbd353d35,0xbd800000,0xbd35bd35,0x8000bd80,0x3d35bd35,0x3d800000,0x3d353d35,0x80003d80,0xbd353d35,
0xbd800000,0xbd35bd35,0x8000bd80,0x3d35bd35,0x3d800000,0x3d353d35,0x80003d80,0xbd353d35,0xbd800000,0xbd35bd35,0x8000bd80,0x3d35bd35,0x3d800000,0x3d353d35,0x80003d80,0xbd353d35,
0xbd35bd35,0x3c48bd7b,0x3d6dbcc4,0x3d553d0e,0x3d800000,0x3d0e3d55,0xbcc43d6d,0xbd7b3c48,0x3d35bd35,0x3d7b3c48,0x3cc43d6d,0xbd0e3d55,0x80003d80,0xbd553d0e,0xbd6dbcc4,0xbc48bd7b,
0x3d353d35,0xbc483d7b,0xbd6d3cc4,0xbd55bd0e,0xbd800000,0xbd0ebd55,0x3cc4bd6d,0x3d7bbc48,0xbd353d35,0xbd7bbc48,0xbcc4bd6d,0x3d0ebd55,0x8000bd80,0x3d55bd0e,0x3d6d3cc4,0x3c483d7b,
0x3d800000,0x3cc43d6d,0xbd353d35,0xbd6dbcc4,0x8000bd80,0x3d6dbcc4,0x3d353d35,0xbcc43d6d,0xbd800000,0xbcc4bd6d,0x3d35bd35,0x3d6d3cc4,0x80003d80,0xbd6d3cc4,0xbd35bd35,0x3cc4bd6d,
0x3d800000,0x3cc43d6d,0xbd353d35,0xbd6dbcc4,0x8000bd80,0x3d6dbcc4,0x3d353d35,0xbcc43d6d,0xbd800000,0xbcc4bd6d,0x3d35bd35,0x3d6d3cc4,0x80003d80,0xbd6d3cc4,0xbd35bd35,0x3cc4bd6d,
0xbd35bd35,0x3d0ebd55,0x3d6d3cc4,0xbc483d7b,0x8000bd80,0x3d7bbc48,0x3cc43d6d,0xbd553d0e,0x3d35bd35,0x3d553d0e,0xbcc43d6d,0xbd7bbc48,0x3d800000,0x3c483d7b,0xbd6d3cc4,0xbd0ebd55,
0x3d353d35,0xbd0e3d55,0xbd6dbcc4,0x3c48bd7b,0x80003d80,0xbd7b3c48,0xbcc4bd6d,0x3d55bd0e,0xbd353d35,0xbd55bd0e,0x3cc4bd6d,0x3d7b3c48,0xbd800000,0xbc48bd7b,0x3d6dbcc4,0x3d0e3d55,
0x3d80,0xbd800000,0xbd80,0x3d800000,0x3d80,0xbd800000,0xbd80,0x3d800000,0x3d80,0xbd800000,0xbd80,0x3d800000,0x3d80,0xbd800000,0xbd80,0x3d800000,
0x3d80,0xbd800000,0xbd80,0x3d800000,0x3d80,0xbd800000,0xbd80,0x3d800000,0x3d80,0xbd800000,0xbd80,0x3d800000,0x3d80,0xbd800000,0xbd80,0x3d800000,
0xbd353d35,0xbd0ebd55,0x3d6dbcc4,0x3c483d7b,0x3d80,0xbd7bbc48,0x3cc4bd6d,0x3d553d0e,0xbd35bd35,0x3d55bd0e,0x3cc43d6d,0xbd7b3c48,0xbd800000,0x3c48bd7b,0x3d6d3cc4,0xbd0e3d55,
0x3d35bd35,0x3d0e3d55,0xbd6d3cc4,0xbc48bd7b,0xbd80,0x3d7b3c48,0xbcc43d6d,0xbd55bd0e,0x3d353d35,0xbd553d0e,0xbcc4bd6d,0x3d7bbc48,0x3d800000,0xbc483d7b,0xbd6dbcc4,0x3d0ebd55,
0xbd80,0x3d6d3cc4,0xbd353d35,0xbcc4bd6d,0x3d800000,0xbcc43d6d,0xbd35bd35,0x3d6dbcc4,0x3d80,0xbd6dbcc4,0x3d35bd35,0x3cc43d6d,0xbd800000,0x3cc4bd6d,0x3d353d35,0xbd6d3cc4,
0xbd80,0x3d6d3cc4,0xbd353d35,0xbcc4bd6d,0x3d800000,0xbcc43d6d,0xbd35bd35,0x3d6dbcc4,0x3d80,0xbd6dbcc4,0x3d35bd35,0x3cc43d6d,0xbd800000,0x3cc4bd6d,0x3d353d35,0xbd6d3cc4,
0xbd353d35,0xbc48bd7b,0x3d6d3cc4,0xbd553d0e,0x3d800000,0xbd0e3d55,0xbcc4bd6d,0x3d7b3c48,0xbd35bd35,0x3d7bbc48,0xbcc43d6d,0xbd0ebd55,0x3d80,0xbd55bd0e,0x3d6dbcc4,0xbc483d7b,
0x3d35bd35,0x3c483d7b,0xbd6dbcc4,0x3d55bd0e,0xbd800000,0x3d0ebd55,0x3cc43d6d,0xbd7bbc48,0x3d353d35,0xbd7b3c48,0x3cc4bd6d,0x3d0e3d55,0xbd80,0x3d553d0e,0xbd6d3cc4,0x3c48bd7b,
0x3d80,0xbd35bd35,0x3d800000,0xbd353d35,0xbd80,0x3d353d35,0xbd800000,0x3d35bd35,0x3d80,0xbd35bd35,0x3d800000,0xbd353d35,0xbd80,0x3d353d35,0xbd800000,0x3d35bd35,
0x3d80,0xbd35bd35,0x3d800000,0xbd353d35,0xbd80,0x3d353d35,0xbd800000,0x3d35bd35,0x3d80,0xbd35bd35,0x3d800000,0xbd353d35,0xbd80,0x3d353d35,0xbd800000,0x3d35bd35,
0xbd353d35,0x3c48bd7b,0x3cc43d6d,0xbd55bd0e,0xbd80,0x3d0e3d55,0xbd6dbcc4,0x3d7bbc48,0xbd35bd35,0x3d7b3c48,0xbd6d3cc4,0x3d0ebd55,0x3d800000,0xbd553d0e,0x3cc4bd6d,0x3c483d7b,
0x3d35bd35,0xbc483d7b,0xbcc4bd6d,0x3d553d0e,0x3d80,0xbd0ebd55,0x3d6d3cc4,0xbd7b3c48,0x3d353d35,0xbd7bbc48,0x3d6dbcc4,0xbd0e3d55,0xbd800000,0x3d55bd0e,0xbcc43d6d,0xbc48bd7b,
0xbd80,0x3cc43d6d,0xbd35bd35,0x3d6d3cc4,0xbd800000,0x3d6dbcc4,0xbd353d35,0x3cc4bd6d,0x3d80,0xbcc4bd6d,0x3d353d35,0xbd6dbcc4,0x3d800000,0xbd6d3cc4,0x3d35bd35,0xbcc43d6d,
0xbd80,0x3cc43d6d,0xbd35bd35,0x3d6d3cc4,0xbd800000,0x3d6dbcc4,0xbd353d35,0x3cc4bd6d,0x3d80,0xbcc4bd6d,0x3d353d35,0xbd6dbcc4,0x3d800000,0xbd6d3cc4,0x3d35bd35,0xbcc43d6d,
0xbd353d35,0x3d0ebd55,0xbcc43d6d,0x3c48bd7b,0xbd800000,0x3d7bbc48,0xbd6d3cc4,0x3d55bd0e,0xbd35bd35,0x3d553d0e,0xbd6dbcc4,0x3d7b3c48,0xbd80,0x3c483d7b,0xbcc4bd6d,0x3d0e3d55,
0x3d35bd35,0xbd0e3d55,0x3cc4bd6d,0xbc483d7b,0x3d800000,0xbd7b3c48,0x3d6dbcc4,0xbd553d0e,0x3d353d35,0xbd55bd0e,0x3d6d3cc4,0xbd7bbc48,0x3d80,0xbc48bd7b,0x3cc43d6d,0xbd0ebd55,
0xbd800000,0x8000bd80,0x3d800000,0x80003d80,0xbd800000,0x8000bd80,0x3d800000,0x80003d80,0xbd800000,0x8000bd80,0x3d800000,0x80003d80,0xbd800000,0x8000bd80,0x3d800000,0x80003d80,
0xbd800000,0x8000bd80,0x3d800000,0x80003d80,0xbd800000,0x8000bd80,0x3d800000,0x80003d80,0xbd800000,0x8000bd80,0x3d800000,0x80003d80,0xbd800000,0x8000bd80,0x3d800000,0x80003d80,
0xbd35bd35,0x3d55bd0e,0x3cc43d6d,0xbd7b3c48,0xbd800000,0x3c48bd7b,0x3d6d3cc4,0xbd0e3d55,0x3d35bd35,0x3d0e3d55,0xbd6d3cc4,0xbc48bd7b,0x8000bd80,0x3d7b3c48,0xbcc43d6d,0xbd55bd0e,
0x3d353d35,0xbd553d0e,0xbcc4bd6d,0x3d7bbc48,0x3d800000,0xbc483d7b,0xbd6dbcc4,0x3d0ebd55,0xbd353d35,0xbd0ebd55,0x3d6dbcc4,0x3c483d7b,0x80003d80,0xbd7bbc48,0x3cc4bd6d,0x3d553d0e,
0x3d800000,0xbcc43d6d,0xbd35bd35,0x3d6dbcc4,0x80003d80,0xbd6dbcc4,0x3d35bd35,0x3cc43d6d,0xbd800000,0x3cc4bd6d,0x3d353d35,0xbd6d3cc4,0x8000bd80,0x3d6d3cc4,0xbd353d35,0xbcc4bd6d,
0x3d800000,0xbcc43d6d,0xbd35bd35,0x3d6dbcc4,0x80003d80,0xbd6dbcc4,0x3d35bd35,0x3cc43d6d,0xbd800000,0x3cc4bd6d,0x3d353d35,0xbd6d3cc4,0x8000bd80,0x3d6d3cc4,0xbd353d35,0xbcc4bd6d,
0xbd35bd35,0x3d7bbc48,0xbcc43d6d,0xbd0ebd55,0x80003d80,0xbd55bd0e,0x3d6dbcc4,0xbc483d7b,0x3d35bd35,0x3c483d7b,0xbd6dbcc4,0x3d55bd0e,0xbd800000,0x3d0ebd55,0x3cc43d6d,0xbd7bbc48,
0x3d353d35,0xbd7b3c48,0x3cc4bd6d,0x3d0e3d55,0x8000bd80,0x3d553d0e,0xbd6d3cc4,0x3c48bd7b,0xbd353d35,0xbc48bd7b,0x3d6d3cc4,0xbd553d0e,0x3d800000,0xbd0e3d55,0xbcc4bd6d,0x3d7b3c48,
0xbd800000,0x3d35bd35,0x80003d80,0xbd35bd35,0x3d800000,0xbd353d35,0x8000bd80,0x3d353d35,0xbd800000,0x3d35bd35,0x80003d80,0xbd35bd35,0x3d800000,0xbd353d35,0x8000bd80,0x3d353d35,
0xbd800000,0x3d35bd35,0x80003d80,0xbd35bd35,0x3d800000,0xbd353d35,0x8000bd80,0x3d353d35,0xbd800000,0x3d35bd35,0x80003d80,0xbd35bd35,0x3d800000,0xbd353d35,0x8000bd80,0x3d353d35,
0xbd35bd35,0x3d7b3c48,0xbd6d3cc4,0x3d0ebd55,0x3d800000,0xbd553d0e,0x3cc4bd6d,0x3c483d7b,0x3d35bd35,0xbc483d7b,0xbcc4bd6d,0x3d553d0e,0x80003d80,0xbd0ebd55,0x3d6d3cc4,0xbd7b3c48,
0x3d353d35,0xbd7bbc48,0x3d6dbcc4,0xbd0e3d55,0xbd800000,0x3d55bd0e,0xbcc43d6d,0xbc48bd7b,0xbd353d35,0x3c48bd7b,0x3cc43d6d,0xbd55bd0e,0x8000bd80,0x3d0e3d55,0xbd6dbcc4,0x3d7bbc48,
0x3d800000,0xbd6d3cc4,0x3d35bd35,0xbcc43d6d,0x8000bd80,0x3cc43d6d,0xbd35bd35,0x3d6d3cc4,0xbd800000,0x3d6dbcc4,0xbd353d35,0x3cc4bd6d,0x80003d80,0xbcc4bd6d,0x3d353d35,0xbd6dbcc4,
0x3d800000,0xbd6d3cc4,0x3d35bd35,0xbcc43d6d,0x8000bd80,0x3cc43d6d,0xbd35bd35,0x3d6d3cc4,0xbd800000,0x3d6dbcc4,0xbd353d35,0x3cc4bd6d,0x80003d80,0xbcc4bd6d,0x3d353d35,0xbd6dbcc4,
0xbd35bd35,0x3d553d0e,0xbd6dbcc4,0x3d7b3c48,0x8000bd80,0x3c483d7b,0xbcc4bd6d,0x3d0e3d55,0x3d35bd35,0xbd0e3d55,0x3cc4bd6d,0xbc483d7b,0x3d800000,0xbd7b3c48,0x3d6dbcc4,0xbd553d0e,
0x3d353d35,0xbd55bd0e,0x3d6d3cc4,0xbd7bbc48,0x80003d80,0xbc48bd7b,0x3cc43d6d,0xbd0ebd55,0xbd353d35,0x3d0ebd55,0xbcc43d6d,0x3c48bd7b,0xbd800000,0x3d7bbc48,0xbd6d3cc4,0x3d55bd0e,
0x3d80,0xbd80,0x3d80,0xbd80,0x3d80,0xbd80,0x3d80,0xbd80,0x3d80,0xbd80,0x3d80,0xbd80,0x3d80,0xbd80,0x3d80,0xbd80,
0x3d80,0xbd80,0x3d80,0xbd80,0x3d80,0xbd80,0x3d80,0xbd80,0x3d80,0xbd80,0x3d80,0xbd80,0x3d80,0xbd80,0x3d80,0xbd80,
0xbd353d35,0x3d55bd0e,0xbd6d3cc4,0x3d7bbc48,0x3d80,0x3c48bd7b,0xbcc43d6d,0x3d0ebd55,0xbd35bd35,0x3d0e3d55,0xbcc4bd6d,0x3c483d7b,0xbd800000,0x3d7b3c48,0xbd6dbcc4,0x3d553d0e,
0x3d35bd35,0xbd553d0e,0x3d6dbcc4,0xbd7b3c48,0xbd80,0xbc483d7b,0x3cc4bd6d,0xbd0e3d55,0x3d353d35,0xbd0ebd55,0x3cc43d6d,0xbc48bd7b,0x3d800000,0xbd7bbc48,0x3d6d3cc4,0xbd55bd0e,
0xbd80,0xbcc43d6d,0x3d35bd35,0xbd6d3cc4,0x3d800000,0xbd6dbcc4,0x3d353d35,0xbcc4bd6d,0x3d80,0x3cc4bd6d,0xbd353d35,0x3d6dbcc4,0xbd800000,0x3d6d3cc4,0xbd35bd35,0x3cc43d6d,
0xbd80,0xbcc43d6d,0x3d35bd35,0xbd6d3cc4,0x3d800000,0xbd6dbcc4,0x3d353d35,0xbcc4bd6d,0x3d80,0x3cc4bd6d,0xbd353d35,0x3d6dbcc4,0xbd800000,0x3d6d3cc4,0xbd35bd35,0x3cc43d6d,
0xbd353d35,0x3d7bbc48,0xbd6dbcc4,0x3d0e3d55,0x3d800000,0xbd55bd0e,0x3cc43d6d,0x3c48bd7b,0xbd35bd35,0x3c483d7b,0x3cc4bd6d,0xbd553d0e,0x3d80,0x3d0ebd55,0xbd6d3cc4,0x3d7b3c48,
0x3d35bd35,0xbd7b3c48,0x3d6d3cc4,0xbd0ebd55,0xbd800000,0x3d553d0e,0xbcc4bd6d,0xbc483d7b,0x3d353d35,0xbc48bd7b,0xbcc43d6d,0x3d55bd0e,0xbd80,0xbd0e3d55,0x3d6dbcc4,0xbd7bbc48,
0x3d80,0x3d35bd35,0xbd800000,0x3d353d35,0xbd80,0xbd353d35,0x3d800000,0xbd35bd35,0x3d80,0x3d35bd35,0xbd800000,0x3d353d35,0xbd80,0xbd353d35,0x3d800000,0xbd35bd35,
0x3d80,0x3d35bd35,0xbd800000,0x3d353d35,0xbd80,0xbd353d35,0x3d800000,0xbd35bd35,0x3d80,0x3d35bd35,0xbd800000,0x3d353d35,0xbd80,0xbd353d35,0x3d800000,0xbd35bd35,
0xbd353d35,0x3d7b3c48,0xbcc4bd6d,0xbd0e3d55,0xbd80,0xbd553d0e,0x3d6d3cc4,0xbc48bd7b,0xbd35bd35,0xbc483d7b,0x3d6dbcc4,0xbd55bd0e,0x3d800000,0xbd0ebd55,0xbcc43d6d,0x3d7bbc48,
0x3d35bd35,0xbd7bbc48,0x3cc43d6d,0x3d0ebd55,0x3d80,0x3d55bd0e,0xbd6dbcc4,0x3c483d7b,0x3d353d35,0x3c48bd7b,0xbd6d3cc4,0x3d553d0e,0xbd800000,0x3d0e3d55,0x3cc4bd6d,0xbd7b3c48,
0xbd80,0xbd6d3cc4,0x3d353d35,0x3cc4bd6d,0xbd800000,0x3cc43d6d,0x3d35bd35,0xbd6dbcc4,0x3d80,0x3d6dbcc4,0xbd35bd35,0xbcc43d6d,0x3d800000,0xbcc4bd6d,0xbd353d35,0x3d6d3cc4,
0xbd80,0xbd6d3cc4,0x3d353d35,0x3cc4bd6d,0xbd800000,0x3cc43d6d,0x3d35bd35,0xbd6dbcc4,0x3d80,0x3d6dbcc4,0xbd35bd35,0xbcc43d6d,0x3d800000,0xbcc4bd6d,0xbd353d35,0x3d6d3cc4,
0xbd353d35,0x3d553d0e,0x3cc4bd6d,0xbd7bbc48,0xbd800000,0x3c483d7b,0x3d6dbcc4,0xbd0ebd55,0xbd35bd35,0xbd0e3d55,0x3d6d3cc4,0x3c48bd7b,0xbd80,0xbd7b3c48,0x3cc43d6d,0x3d55bd0e,
0x3d35bd35,0xbd55bd0e,0xbcc43d6d,0x3d7b3c48,0x3d800000,0xbc48bd7b,0xbd6d3cc4,0x3d0e3d55,0x3d353d35,0x3d0ebd55,0xbd6dbcc4,0xbc483d7b,0x3d80,0x3d7bbc48,0xbcc4bd6d,0xbd553d0e,
0xbd800000,0x3d800000,0xbd800000,0x3d800000,0xbd800000,0x3d800000,0xbd800000,0x3d800000,0xbd800000,0x3d800000,0xbd800000,0x3d800000,0xbd800000,0x3d800000,0xbd800000,0x3d800000,
0xbd800000,0x3d800000,0xbd800000,0x3d800000,0xbd800000,0x3d800000,0xbd800000,0x3d800000,0xbd800000,0x3d800000,0xbd800000,0x3d800000,0xbd800000,0x3d800000,0xbd800000,0x3d800000,
0xbd35bd35,0x3d0e3d55,0xbcc4bd6d,0x3c483d7b,0xbd800000,0x3d7b3c48,0xbd6dbcc4,0x3d553d0e,0x3d35bd35,0xbd553d0e,0x3d6dbcc4,0xbd7b3c48,0x8000bd80,0xbc483d7b,0x3cc4bd6d,0xbd0e3d55,
0x3d353d35,0xbd0ebd55,0x3cc43d6d,0xbc48bd7b,0x3d800000,0xbd7bbc48,0x3d6d3cc4,0xbd55bd0e,0xbd353d35,0x3d55bd0e,0xbd6d3cc4,0x3d7bbc48,0x80003d80,0x3c48bd7b,0xbcc43d6d,0x3d0ebd55,
0x3d800000,0xbd6dbcc4,0x3d353d35,0xbcc4bd6d,0x80003d80,0x3cc4bd6d,0xbd353d35,0x3d6dbcc4,0xbd800000,0x3d6d3cc4,0xbd35bd35,0x3cc43d6d,0x8000bd80,0xbcc43d6d,0x3d35bd35,0xbd6d3cc4,
0x3d800000,0xbd6dbcc4,0x3d353d35,0xbcc4bd6d,0x80003d80,0x3cc4bd6d,0xbd353d35,0x3d6dbcc4,0xbd800000,0x3d6d3cc4,0xbd35bd35,0x3cc43d6d,0x8000bd80,0xbcc43d6d,0x3d35bd35,0xbd6d3cc4,
0xbd35bd35,0x3c483d7b,0x3cc4bd6d,0xbd553d0e,0x80003d80,0x3d0ebd55,0xbd6d3cc4,0x3d7b3c48,0x3d35bd35,0xbd7b3c48,0x3d6d3cc4,0xbd0ebd55,0xbd800000,0x3d553d0e,0xbcc4bd6d,0xbc483d7b,
0x3d353d35,0xbc48bd7b,0xbcc43d6d,0x3d55bd0e,0x8000bd80,0xbd0e3d55,0x3d6dbcc4,0xbd7bbc48,0xbd353d35,0x3d7bbc48,0xbd6dbcc4,0x3d0e3d55,0x3d800000,0xbd55bd0e,0x3cc43d6d,0x3c48bd7b,
0xbd800000,0x3d353d35,0x8000bd80,0xbd353d35,0x3d800000,0xbd35bd35,0x80003d80,0x3d35bd35,0xbd800000,0x3d353d35,0x8000bd80,0xbd353d35,0x3d800000,0xbd35bd35,0x80003d80,0x3d35bd35,
0xbd800000,0x3d353d35,0x8000bd80,0xbd353d35,0x3d800000,0xbd35bd35,0x80003d80,0x3d35bd35,0xbd800000,0x3d353d35,0x8000bd80,0xbd353d35,0x3d800000,0xbd35bd35,0x80003d80,0x3d35bd35,
0xbd35bd35,0xbc483d7b,0x3d6dbcc4,0xbd55bd0e,0x3d800000,0xbd0ebd55,0xbcc43d6d,0x3d7bbc48,0x3d35bd35,0xbd7bbc48,0x3cc43d6d,0x3d0ebd55,0x80003d80,0x3d55bd0e,0xbd6dbcc4,0x3c483d7b,
0x3d353d35,0x3c48bd7b,0xbd6d3cc4,0x3d553d0e,0xbd800000,0x3d0e3d55,0x3cc4bd6d,0xbd7b3c48,0xbd353d35,0x3d7b3c48,0xbcc4bd6d,0xbd0e3d55,0x8000bd80,0xbd553d0e,0x3d6d3cc4,0xbc48bd7b,
0x3d800000,0xbcc4bd6d,0xbd353d35,0x3d6d3cc4,0x8000bd80,0xbd6d3cc4,0x3d353d35,0x3cc4bd6d,0xbd800000,0x3cc43d6d,0x3d35bd35,0xbd6dbcc4,0x80003d80,0x3d6dbcc4,0xbd35bd35,0xbcc43d6d,
0x3d800000,0xbcc4bd6d,0xbd353d35,0x3d6d3cc4,0x8000bd80,0xbd6d3cc4,0x3d353d35,0x3cc4bd6d,0xbd800000,0x3cc43d6d,0x3d35bd35,0xbd6dbcc4,0x80003d80,0x3d6dbcc4,0xbd35bd35,0xbcc43d6d,
0xbd35bd35,0xbd0e3d55,0x3d6d3cc4,0x3c48bd7b,0x8000bd80,0xbd7b3c48,0x3cc43d6d,0x3d55bd0e,0x3d35bd35,0xbd55bd0e,0xbcc43d6d,0x3d7b3c48,0x3d800000,0xbc48bd7b,0xbd6d3cc4,0x3d0e3d55,
0x3d353d35,0x3d0ebd55,0xbd6dbcc4,0xbc483d7b,0x80003d80,0x3d7bbc48,0xbcc4bd6d,0xbd553d0e,0xbd353d35,0x3d553d0e,0x3cc4bd6d,0xbd7bbc48,0xbd800000,0x3c483d7b,0x3d6dbcc4,0xbd0ebd55,
0x3d80,0x3d800000,0xbd80,0xbd800000,0x3d80,0x3d800000,0xbd80,0xbd800000,0x3d80,0x3d800000,0xbd80,0xbd800000,0x3d80,0x3d800000,0xbd80,0xbd800000,
0x3d80,0x3d800000,0xbd80,0xbd800000,0x3d80,0x3d800000,0xbd80,0xbd800000,0x3d80,0x3d800000,0xbd80,0xbd800000,0x3d80,0x3d800000,0xbd80,0xbd800000,
0xbd353d35,0x3d0e3d55,0x3d6dbcc4,0xbc48bd7b,0x3d80,0x3d7b3c48,0x3cc4bd6d,0xbd55bd0e,0xbd35bd35,0xbd553d0e,0x3cc43d6d,0x3d7bbc48,0xbd800000,0xbc483d7b,0x3d6d3cc4,0x3d0ebd55,
0x3d35bd35,0xbd0ebd55,0xbd6d3cc4,0x3c483d7b,0xbd80,0xbd7bbc48,0xbcc43d6d,0x3d553d0e,0x3d353d35,0x3d55bd0e,0xbcc4bd6d,0xbd7b3c48,0x3d800000,0x3c48bd7b,0xbd6dbcc4,0xbd0e3d55,
0xbd80,0xbd6dbcc4,0xbd353d35,0x3cc43d6d,0x3d800000,0x3cc4bd6d,0xbd35bd35,0xbd6d3cc4,0x3d80,0x3d6d3cc4,0x3d35bd35,0xbcc4bd6d,0xbd800000,0xbcc43d6d,0x3d353d35,0x3d6dbcc4,
0xbd80,0xbd6dbcc4,0xbd353d35,0x3cc43d6d,0x3d800000,0x3cc4bd6d,0xbd35bd35,0xbd6d3cc4,0x3d80,0x3d6d3cc4,0x3d35bd35,0xbcc4bd6d,0xbd800000,0xbcc43d6d,0x3d353d35,0x3d6dbcc4,
0xbd353d35,0x3c483d7b,0x3d6d3cc4,0x3d55bd0e,0x3d800000,0x3d0ebd55,0xbcc4bd6d,0xbd7bbc48,0xbd35bd35,0xbd7b3c48,0xbcc43d6d,0x3d0e3d55,0x3d80,0x3d553d0e,0x3d6dbcc4,0x3c48bd7b,
0x3d35bd35,0xbc48bd7b,0xbd6dbcc4,0xbd553d0e,0xbd800000,0xbd0e3d55,0x3cc43d6d,0x3d7b3c48,0x3d353d35,0x3d7bbc48,0x3cc4bd6d,0xbd0ebd55,0xbd80,0xbd55bd0e,0xbd6d3cc4,0xbc483d7b,
0x3d80,0x3d353d35,0x3d800000,0x3d35bd35,0xbd80,0xbd35bd35,0xbd800000,0xbd353d35,0x3d80,0x3d353d35,0x3d800000,0x3d35bd35,0xbd80,0xbd35bd35,0xbd800000,0xbd353d35,
0x3d80,0x3d353d35,0x3d800000,0x3d35bd35,0xbd80,0xbd35bd35,0xbd800000,0xbd353d35,0x3d80,0x3d353d35,0x3d800000,0x3d35bd35,0xbd80,0xbd35bd35,0xbd800000,0xbd353d35,
0xbd353d35,0xbc483d7b,0x3cc43d6d,0x3d553d0e,0xbd80,0xbd0ebd55,0xbd6dbcc4,0xbd7b3c48,0xbd35bd35,0xbd7bbc48,0xbd6d3cc4,0xbd0e3d55,0x3d800000,0x3d55bd0e,0x3cc4bd6d,0xbc48bd7b,
0x3d35bd35,0x3c48bd7b,0xbcc4bd6d,0xbd55bd0e,0x3d80,0x3d0e3d55,0x3d6d3cc4,0x3d7bbc48,0x3d353d35,0x3d7b3c48,0x3d6dbcc4,0x3d0ebd55,0xbd800000,0xbd553d0e,0xbcc43d6d,0x3c483d7b,
0xbd80,0xbcc4bd6d,0xbd35bd35,0xbd6dbcc4,0xbd800000,0xbd6d3cc4,0xbd353d35,0xbcc43d6d,0x3d80,0x3cc43d6d,0x3d353d35,0x3d6d3cc4,0x3d800000,0x3d6dbcc4,0x3d35bd35,0x3cc4bd6d,
0xbd80,0xbcc4bd6d,0xbd35bd35,0xbd6dbcc4,0xbd800000,0xbd6d3cc4,0xbd353d35,0xbcc43d6d,0x3d80,0x3cc43d6d,0x3d353d35,0x3d6d3cc4,0x3d800000,0x3d6dbcc4,0x3d35bd35,0x3cc4bd6d,
0xbd353d35,0xbd0e3d55,0xbcc43d6d,0xbc483d7b,0xbd800000,0xbd7b3c48,0xbd6d3cc4,0xbd553d0e,0xbd35bd35,0xbd55bd0e,0xbd6dbcc4,0xbd7bbc48,0xbd80,0xbc48bd7b,0xbcc4bd6d,0xbd0ebd55,
0x3d35bd35,0x3d0ebd55,0x3cc4bd6d,0x3c48bd7b,0x3d800000,0x3d7bbc48,0x3d6dbcc4,0x3d55bd0e,0x3d353d35,0x3d553d0e,0x3d6d3cc4,0x3d7b3c48,0x3d80,0x3c483d7b,0x3cc43d6d,0x3d0e3d55,
0xbd800000,0x80003d80,0x3d800000,0x8000bd80,0xbd800000,0x80003d80,0x3d800000,0x8000bd80,0xbd800000,0x80003d80,0x3d800000,0x8000bd80,0xbd800000,0x80003d80,0x3d800000,0x8000bd80,
0xbd800000,0x80003d80,0x3d800000,0x8000bd80,0xbd800000,0x80003d80,0x3d800000,0x8000bd80,0xbd800000,0x80003d80,0x3d800000,0x8000bd80,0xbd800000,0x80003d80,0x3d800000,0x8000bd80,
0xbd35bd35,0xbd553d0e,0x3cc43d6d,0x3d7bbc48,0xbd800000,0xbc483d7b,0x3d6d3cc4,0x3d0ebd55,0x3d35bd35,0xbd0ebd55,0xbd6d3cc4,0x3c483d7b,0x8000bd80,0xbd7bbc48,0xbcc43d6d,0x3d553d0e,
0x3d353d35,0x3d55bd0e,0xbcc4bd6d,0xbd7b3c48,0x3d800000,0x3c48bd7b,0xbd6dbcc4,0xbd0e3d55,0xbd353d35,0x3d0e3d55,0x3d6dbcc4,0xbc48bd7b,0x80003d80,0x3d7b3c48,0x3cc4bd6d,0xbd55bd0e,
0x3d800000,0x3cc4bd6d,0xbd35bd35,0xbd6d3cc4,0x80003d80,0x3d6d3cc4,0x3d35bd35,0xbcc4bd6d,0xbd800000,0xbcc43d6d,0x3d353d35,0x3d6dbcc4,0x8000bd80,0xbd6dbcc4,0xbd353d35,0x3cc43d6d,
0x3d800000,0x3cc4bd6d,0xbd35bd35,0xbd6d3cc4,0x80003d80,0x3d6d3cc4,0x3d35bd35,0xbcc4bd6d,0xbd800000,0xbcc43d6d,0x3d353d35,0x3d6dbcc4,0x8000bd80,0xbd6dbcc4,0xbd353d35,0x3cc43d6d,
0xbd35bd35,0xbd7b3c48,0xbcc43d6d,0x3d0e3d55,0x80003d80,0x3d553d0e,0x3d6dbcc4,0x3c48bd7b,0x3d35bd35,0xbc48bd7b,0xbd6dbcc4,0xbd553d0e,0xbd800000,0xbd0e3d55,0x3cc43d6d,0x3d7b3c48,
0x3d353d35,0x3d7bbc48,0x3cc4bd6d,0xbd0ebd55,0x8000bd80,0xbd55bd0e,0xbd6d3cc4,0xbc483d7b,0xbd353d35,0x3c483d7b,0x3d6d3cc4,0x3d55bd0e,0x3d800000,0x3d0ebd55,0xbcc4bd6d,0xbd7bbc48,
0xbd800000,0xbd353d35,0x80003d80,0x3d353d35,0x3d800000,0x3d35bd35,0x8000bd80,0xbd35bd35,0xbd800000,0xbd353d35,0x80003d80,0x3d353d35,0x3d800000,0x3d35bd35,0x8000bd80,0xbd35bd35,
0xbd800000,0xbd353d35,0x80003d80,0x3d353d35,0x3d800000,0x3d35bd35,0x8000bd80,0xbd35bd35,0xbd800000,0xbd353d35,0x80003d80,0x3d353d35,0x3d800000,0x3d35bd35,0x8000bd80,0xbd35bd35,
0xbd35bd35,0xbd7bbc48,0xbd6d3cc4,0xbd0e3d55,0x3d800000,0x3d55bd0e,0x3cc4bd6d,0xbc48bd7b,0x3d35bd35,0x3c48bd7b,0xbcc4bd6d,0xbd55bd0e,0x80003d80,0x3d0e3d55,0x3d6d3cc4,0x3d7bbc48,
0x3d353d35,0x3d7b3c48,0x3d6dbcc4,0x3d0ebd55,0xbd800000,0xbd553d0e,0xbcc43d6d,0x3c483d7b,0xbd353d35,0xbc483d7b,0x3cc43d6d,0x3d553d0e,0x8000bd80,0xbd0ebd55,0xbd6dbcc4,0xbd7b3c48,
0x3d800000,0x3d6dbcc4,0x3d35bd35,0x3cc4bd6d,0x8000bd80,0xbcc4bd6d,0xbd35bd35,0xbd6dbcc4,0xbd800000,0xbd6d3cc4,0xbd353d35,0xbcc43d6d,0x80003d80,0x3cc43d6d,0x3d353d35,0x3d6d3cc4,
0x3d800000,0x3d6dbcc4,0x3d35bd35,0x3cc4bd6d,0x8000bd80,0xbcc4bd6d,0xbd35bd35,0xbd6dbcc4,0xbd800000,0xbd6d3cc4,0xbd353d35,0xbcc43d6d,0x80003d80,0x3cc43d6d,0x3d353d35,0x3d6d3cc4,
0xbd35bd35,0xbd55bd0e,0xbd6dbcc4,0xbd7bbc48,0x8000bd80,0xbc48bd7b,0xbcc4bd6d,0xbd0ebd55,0x3d35bd35,0x3d0ebd55,0x3cc4bd6d,0x3c48bd7b,0x3d800000,0x3d7bbc48,0x3d6dbcc4,0x3d55bd0e,
0x3d353d35,0x3d553d0e,0x3d6d3cc4,0x3d7b3c48,0x80003d80,0x3c483d7b,0x3cc43d6d,0x3d0e3d55,0xbd353d35,0xbd0e3d55,0xbcc43d6d,0xbc483d7b,0xbd800000,0xbd7b3c48,0xbd6d3cc4,0xbd553d0e,
0x3d80,0xbb493d80,0xbbc93d7f,0xbc163d7d,0xbc483d7b,0xbc793d78,0xbc953d75,0xbcac3d71,0xbcc43d6d,0xbcdb3d67,0xbcf13d62,0xbd043d5c,0xbd0e3d55,0xbd183d4e,0xbd223d46,0xbd2c3d3e,
0xbd353d35,0xbd3e3d2c,0xbd463d22,0xbd4e3d18,0xbd553d0e,0xbd5c3d04,0xbd623cf1,0xbd673cdb,0xbd6d3cc4,0xbd713cac,0xbd753c95,0xbd783c79,0xbd7b3c48,0xbd7d3c16,0xbd7f3bc9,0xbd803b49,
0xbd553d0e,0xbd713cac,0xbd7f3bc9,0xbd7dbc16,0x3d80,0xbc793d78,0xbcf13d62,0xbd2c3d3e,0xbc48bd7b,0x3b49bd80,0x3c95bd75,0x3d04bd5c,0xbd6dbcc4,0xbd4ebd18,0xbd22bd46,0xbcdbbd67,
0x3d7b3c48,0x3d673cdb,0x3d463d22,0x3d183d4e,0x3d35bd35,0x3d5cbd04,0x3d75bc95,0x3d80bb49,0xbd0e3d55,0xbd3e3d2c,0xbd623cf1,0xbd783c79,0x3cc43d6d,0x3c163d7d,0xbbc93d7f,0xbcac3d71,
0x3cc4bd6d,0x3d3ebd2c,0x3d75bc95,0x3d7d3c16,0x3d553d0e,0x3d043d5c,0x3bc93d7f,0xbcac3d71,0x3d80,0xbcdb3d67,0xbd463d22,0xbd783c79,0xbd7bbc48,0xbd4ebd18,0xbcf1bd62,0xbb49bd80,
0x3d6dbcc4,0x3d803b49,0x3d623cf1,0x3d183d4e,0x3c483d7b,0xbc793d78,0xbd223d46,0xbd673cdb,0xbd353d35,0xbd713cac,0xbd7fbbc9,0xbd5cbd04,0xbd0ebd55,0xbc16bd7d,0x3c95bd75,0x3d2cbd3e,
0xbd7b3c48,0xbd67bcdb,0xbcf1bd62,0x3c16bd7d,0x3d6d3cc4,0x3d043d5c,0xbbc93d7f,0xbd2c3d3e,0xbd0ebd55,0x3b49bd80,0x3d22bd46,0x3d78bc79,0x3d80,0xbd183d4e,0xbd753c95,0xbd71bcac,
0x3d553d0e,0x3cac3d71,0xbc953d75,0xbd4e3d18,0xbcc4bd6d,0x3c79bd78,0x3d46bd22,0x3d80bb49,0xbc483d7b,0xbd3e3d2c,0xbd7f3bc9,0xbd5cbd04,0x3d35bd35,0x3d7dbc16,0x3d623cf1,0x3cdb3d67,
0xbd353d35,0xbd80bb49,0xbd22bd46,0x3c16bd7d,0x3d55bd0e,0x3d783c79,0x3cf13d62,0xbcac3d71,0xbd6d3cc4,0xbd67bcdb,0xbc95bd75,0x3d04bd5c,0x3d7bbc48,0x3d4e3d18,0x3bc93d7f,0xbd2c3d3e,
0x3d80,0xbd3e3d2c,0xbd7fbbc9,0xbd18bd4e,0x3c48bd7b,0x3d5cbd04,0x3d753c95,0x3cdb3d67,0xbcc43d6d,0xbd713cac,0xbd62bcf1,0xbc79bd78,0x3d0ebd55,0x3d7dbc16,0x3d463d22,0x3b493d80,
0xbd7bbc48,0xbcacbd71,0x3d22bd46,0x3d7d3c16,0x3d35bd35,0x3d783c79,0x3c953d75,0xbd2c3d3e,0x3d0ebd55,0x3d803b49,0x3cf13d62,0xbd043d5c,0x3cc43d6d,0xbd183d4e,0xbd7fbbc9,0xbcdbbd67,
0x3d55bd0e,0x3d673cdb,0x3bc93d7f,0xbd4e3d18,0x3d80,0xbd5c3d04,0xbd62bcf1,0xbb49bd80,0x3c483d7b,0xbd3e3d2c,0xbd75bc95,0xbc79bd78,0xbd6dbcc4,0xbc16bd7d,0x3d46bd22,0x3d713cac,
0x3d6dbcc4,0x3d2c3d3e,0xbcf13d62,0xbd7dbc16,0xbc48bd7b,0x3d5cbd04,0x3d463d22,0xbcac3d71,0xbd353d35,0xbd67bcdb,0x3bc9bd7f,0x3d78bc79,0x3d0e3d55,0xbd183d4e,0xbd75bc95,0xbb49bd80,
0x3cc4bd6d,0x3d803b49,0x3c953d75,0xbd4e3d18,0xbd55bd0e,0x3c79bd78,0x3d7fbbc9,0x3cdb3d67,0x3d80,0xbd713cac,0xbd22bd46,0x3d04bd5c,0x3d7b3c48,0x3c163d7d,0xbd623cf1,0xbd3ebd2c,
0xbd55bd0e,0x3cdbbd67,0x3d753c95,0xbc163d7d,0xbcc4bd6d,0x3d5cbd04,0x3d223d46,0xbd2c3d3e,0x3c48bd7b,0x3d803b49,0x3bc93d7f,0xbd783c79,0x3d35bd35,0x3d4e3d18,0xbcf13d62,0xbd71bcac,
0x3d7bbc48,0x3cac3d71,0xbd623cf1,0xbd18bd4e,0x3d6d3cc4,0xbc793d78,0xbd7fbbc9,0xbb49bd80,0x3d0e3d55,0xbd3e3d2c,0xbd46bd22,0x3d04bd5c,0x3d80,0xbd7d3c16,0xbc95bd75,0x3d67bcdb,
0xbd800000,0xbd80bb49,0xbd7fbbc9,0xbd7dbc16,0xbd7bbc48,0xbd78bc79,0xbd75bc95,0xbd71bcac,0xbd6dbcc4,0xbd67bcdb,0xbd62bcf1,0xbd5cbd04,0xbd55bd0e,0xbd4ebd18,0xbd46bd22,0xbd3ebd2c,
0xbd35bd35,0xbd2cbd3e,0xbd22bd46,0xbd18bd4e,0xbd0ebd55,0xbd04bd5c,0xbcf1bd62,0xbcdbbd67,0xbcc4bd6d,0xbcacbd71,0xbc95bd75,0xbc79bd78,0xbc48bd7b,0xbc16bd7d,0xbbc9bd7f,0xbb49bd80,
0xbd0ebd55,0xbcacbd71,0xbbc9bd7f,0x3c16bd7d,0xbd800000,0xbd78bc79,0xbd62bcf1,0xbd3ebd2c,0x3d7bbc48,0x3d803b49,0x3d753c95,0x3d5c3d04,0x3cc4bd6d,0x3d18bd4e,0x3d46bd22,0x3d67bcdb,
0xbc483d7b,0xbcdb3d67,0xbd223d46,0xbd4e3d18,0x3d353d35,0x3d043d5c,0x3c953d75,0x3b493d80,0xbd55bd0e,0xbd2cbd3e,0xbcf1bd62,0xbc79bd78,0xbd6d3cc4,0xbd7d3c16,0xbd7fbbc9,0xbd71bcac,
0x3d6d3cc4,0x3d2c3d3e,0x3c953d75,0xbc163d7d,0xbd0e3d55,0xbd5c3d04,0xbd7f3bc9,0xbd71bcac,0xbd800000,0xbd67bcdb,0xbd22bd46,0xbc79bd78,0x3c48bd7b,0x3d18bd4e,0x3d62bcf1,0x3d80bb49,
0x3cc43d6d,0xbb493d80,0xbcf13d62,0xbd4e3d18,0xbd7b3c48,0xbd78bc79,0xbd46bd22,0xbcdbbd67,0xbd35bd35,0xbcacbd71,0x3bc9bd7f,0x3d04bd5c,0x3d55bd0e,0x3d7dbc16,0x3d753c95,0x3d3e3d2c,
0xbc48bd7b,0x3cdbbd67,0x3d62bcf1,0x3d7d3c16,0xbcc43d6d,0xbd5c3d04,0xbd7fbbc9,0xbd3ebd2c,0x3d55bd0e,0x3d803b49,0x3d463d22,0x3c793d78,0xbd800000,0xbd4ebd18,0xbc95bd75,0x3cacbd71,
0xbd0e3d55,0xbd713cac,0xbd75bc95,0xbd18bd4e,0x3d6dbcc4,0x3d783c79,0x3d223d46,0x3b493d80,0xbd7bbc48,0xbd2cbd3e,0xbbc9bd7f,0x3d04bd5c,0x3d353d35,0x3c163d7d,0xbcf13d62,0xbd673cdb,
0xbd35bd35,0x3b49bd80,0x3d46bd22,0x3d7d3c16,0x3d0e3d55,0xbc793d78,0xbd623cf1,0xbd71bcac,0xbcc4bd6d,0x3cdbbd67,0x3d75bc95,0x3d5c3d04,0x3c483d7b,0xbd183d4e,0xbd7f3bc9,0xbd3ebd2c,
0xbd800000,0xbd2cbd3e,0x3bc9bd7f,0x3d4ebd18,0x3d7b3c48,0x3d043d5c,0xbc953d75,0xbd673cdb,0xbd6dbcc4,0xbcacbd71,0x3cf1bd62,0x3d78bc79,0x3d553d0e,0x3c163d7d,0xbd223d46,0xbd803b49,
0x3c48bd7b,0x3d71bcac,0x3d463d22,0xbc163d7d,0x3d353d35,0xbc793d78,0xbd753c95,0xbd3ebd2c,0x3d553d0e,0xbb493d80,0xbd623cf1,0xbd5cbd04,0xbd6d3cc4,0xbd4ebd18,0x3bc9bd7f,0x3d67bcdb,
0x3d0e3d55,0xbcdb3d67,0xbd7f3bc9,0xbd18bd4e,0xbd800000,0xbd04bd5c,0x3cf1bd62,0x3d80bb49,0xbd7b3c48,0xbd2cbd3e,0x3c95bd75,0x3d78bc79,0x3cc4bd6d,0x3d7dbc16,0x3d223d46,0xbcac3d71,
0x3cc43d6d,0xbd3e3d2c,0xbd62bcf1,0x3c16bd7d,0x3d7bbc48,0x3d043d5c,0xbd223d46,0xbd71bcac,0xbd35bd35,0x3cdbbd67,0x3d7f3bc9,0x3c793d78,0xbd553d0e,0xbd4ebd18,0x3c95bd75,0x3d80bb49,
0x3d6d3cc4,0xbb493d80,0xbd753c95,0xbd18bd4e,0x3d0ebd55,0x3d783c79,0x3bc93d7f,0xbd673cdb,0xbd800000,0xbcacbd71,0x3d46bd22,0x3d5c3d04,0xbc483d7b,0xbd7d3c16,0xbcf1bd62,0x3d2cbd3e,
0x3d0ebd55,0x3d673cdb,0xbc953d75,0xbd7dbc16,0x3d6dbcc4,0x3d043d5c,0xbd463d22,0xbd3ebd2c,0x3d7b3c48,0xbb493d80,0xbd7f3bc9,0xbc79bd78,0x3d353d35,0xbd183d4e,0xbd62bcf1,0x3cacbd71,
0x3c483d7b,0xbd713cac,0xbcf1bd62,0x3d4ebd18,0xbcc43d6d,0xbd78bc79,0x3bc9bd7f,0x3d80bb49,0xbd553d0e,0xbd2cbd3e,0x3d22bd46,0x3d5c3d04,0xbd800000,0xbc16bd7d,0x3d75bc95,0x3cdb3d67,
0x3d80,0xbd80bb49,0x3bc9bd7f,0x3d7d3c16,0xbc483d7b,0xbd78bc79,0x3c95bd75,0x3d713cac,0xbcc43d6d,0xbd67bcdb,0x3cf1bd62,0x3d5c3d04,0xbd0e3d55,0xbd4ebd18,0x3d22bd46,0x3d3e3d2c,
0xbd353d35,0xbd2cbd3e,0x3d46bd22,0x3d183d4e,0xbd553d0e,0xbd04bd5c,0x3d62bcf1,0x3cdb3d67,0xbd6d3cc4,0xbcacbd71,0x3d75bc95,0x3c793d78,0xbd7b3c48,0xbc16bd7d,0x3d7fbbc9,0x3b493d80,
0xbd553d0e,0xbcacbd71,0x3d7fbbc9,0xbc163d7d,0x3d80,0xbd78bc79,0x3cf1bd62,0x3d3e3d2c,0xbc48bd7b,0x3d803b49,0xbc953d75,0xbd5cbd04,0xbd6dbcc4,0x3d18bd4e,0x3d223d46,0xbd673cdb,
0x3d7b3c48,0xbcdb3d67,0xbd46bd22,0x3d4ebd18,0x3d35bd35,0x3d043d5c,0xbd753c95,0xbb49bd80,0xbd0e3d55,0xbd2cbd3e,0x3d62bcf1,0x3c793d78,0x3cc43d6d,0xbd7d3c16,0x3bc9bd7f,0x3d713cac,
0x3cc4bd6d,0x3d2c3d3e,0xbd753c95,0x3c16bd7d,0x3d553d0e,0xbd5c3d04,0xbbc9bd7f,0x3d713cac,0x3d80,0xbd67bcdb,0x3d46bd22,0x3c793d78,0xbd7bbc48,0x3d18bd4e,0x3cf13d62,0xbd803b49,
0x3d6dbcc4,0xbb493d80,0xbd62bcf1,0x3d4ebd18,0x3c483d7b,0xbd78bc79,0x3d22bd46,0x3cdb3d67,0xbd353d35,0xbcacbd71,0x3d7f3bc9,0xbd043d5c,0xbd0ebd55,0x3d7dbc16,0xbc953d75,0xbd3ebd2c,
0xbd7b3c48,0x3cdbbd67,0x3cf13d62,0xbd7dbc16,0x3d6d3cc4,0xbd5c3d04,0x3bc9bd7f,0x3d3e3d2c,0xbd0ebd55,0x3d803b49,0xbd223d46,0xbc79bd78,0x3d80,0xbd4ebd18,0x3d75bc95,0xbcac3d71,
0x3d553d0e,0xbd713cac,0x3c95bd75,0x3d183d4e,0xbcc4bd6d,0x3d783c79,0xbd463d22,0xbb49bd80,0xbc483d7b,0xbd2cbd3e,0x3d7fbbc9,0xbd043d5c,0x3d35bd35,0x3c163d7d,0xbd62bcf1,0x3d67bcdb,
0xbd353d35,0x3b49bd80,0x3d223d46,0xbd7dbc16,0x3d55bd0e,0xbc793d78,0xbcf1bd62,0x3d713cac,0xbd6d3cc4,0x3cdbbd67,0x3c953d75,0xbd5cbd04,0x3d7bbc48,0xbd183d4e,0xbbc9bd7f,0x3d3e3d2c,
0x3d80,0xbd2cbd3e,0x3d7f3bc9,0xbd4e3d18,0x3c48bd7b,0x3d043d5c,0xbd75bc95,0x3d67bcdb,0xbcc43d6d,0xbcacbd71,0x3d623cf1,0xbd783c79,0x3d0ebd55,0x3c163d7d,0xbd46bd22,0x3d80bb49,
0xbd7bbc48,0x3d71bcac,0xbd223d46,0x3c16bd7d,0x3d35bd35,0xbc793d78,0xbc95bd75,0x3d3e3d2c,0x3d0ebd55,0xbb493d80,0xbcf1bd62,0x3d5c3d04,0x3cc43d6d,0xbd4ebd18,0x3d7f3bc9,0xbd673cdb,
0x3d55bd0e,0xbcdb3d67,0xbbc9bd7f,0x3d183d4e,0x3d80,0xbd04bd5c,0x3d623cf1,0xbd803b49,0x3c483d7b,0xbd2cbd3e,0x3d753c95,0xbd783c79,0xbd6dbcc4,0x3d7dbc16,0xbd463d22,0x3cacbd71,
0x3d6dbcc4,0xbd3e3d2c,0x3cf1bd62,0xbc163d7d,0xbc48bd7b,0x3d043d5c,0xbd46bd22,0x3d713cac,0xbd353d35,0x3cdbbd67,0xbbc93d7f,0xbc79bd78,0x3d0e3d55,0xbd4ebd18,0x3d753c95,0xbd803b49,
0x3cc4bd6d,0xbb493d80,0xbc95bd75,0x3d183d4e,0xbd55bd0e,0x3d783c79,0xbd7f3bc9,0x3d67bcdb,0x3d80,0xbcacbd71,0x3d223d46,0xbd5cbd04,0x3d7b3c48,0xbd7d3c16,0x3d62bcf1,0xbd2c3d3e,
0xbd55bd0e,0x3d673cdb,0xbd75bc95,0x3d7d3c16,0xbcc4bd6d,0x3d043d5c,0xbd22bd46,0x3d3e3d2c,0x3c48bd7b,0xbb493d80,0xbbc9bd7f,0x3c793d78,0x3d35bd35,0xbd183d4e,0x3cf1bd62,0xbcac3d71,
0x3d7bbc48,0xbd713cac,0x3d62bcf1,0xbd4e3d18,0x3d6d3cc4,0xbd78bc79,0x3d7f3bc9,0xbd803b49,0x3d0e3d55,0xbd2cbd3e,0x3d463d22,0xbd5cbd04,0x3d80,0xbc16bd7d,0x3c953d75,0xbcdbbd67,
0xbd800000,0x3b49bd80,0x3d7f3bc9,0xbc163d7d,0xbd7bbc48,0x3c79bd78,0x3d753c95,0xbcac3d71,0xbd6dbcc4,0x3cdbbd67,0x3d623cf1,0xbd043d5c,0xbd55bd0e,0x3d18bd4e,0x3d463d22,0xbd2c3d3e,
0xbd35bd35,0x3d3ebd2c,0x3d223d46,0xbd4e3d18,0xbd0ebd55,0x3d5cbd04,0x3cf13d62,0xbd673cdb,0xbcc4bd6d,0x3d71bcac,0x3c953d75,0xbd783c79,0xbc48bd7b,0x3d7dbc16,0x3bc93d7f,0xbd803b49,
0xbd0ebd55,0x3d71bcac,0x3bc93d7f,0xbd7dbc16,0xbd800000,0x3c79bd78,0x3d623cf1,0xbd2c3d3e,0x3d7bbc48,0xbb493d80,0xbd75bc95,0x3d04bd5c,0x3cc4bd6d,0x3d4e3d18,0xbd463d22,0xbcdbbd67,
0xbc483d7b,0xbd67bcdb,0x3d22bd46,0x3d183d4e,0x3d353d35,0xbd5c3d04,0xbc95bd75,0x3d80bb49,0xbd55bd0e,0x3d3ebd2c,0x3cf13d62,0xbd783c79,0xbd6d3cc4,0xbc16bd7d,0x3d7f3bc9,0xbcac3d71,
0x3d6d3cc4,0xbd3e3d2c,0xbc95bd75,0x3d7d3c16,0xbd0e3d55,0xbd04bd5c,0x3d7fbbc9,0xbcac3d71,0xbd800000,0x3cdbbd67,0x3d223d46,0xbd783c79,0x3c48bd7b,0x3d4e3d18,0xbd623cf1,0xbb49bd80,
0x3cc43d6d,0xbd80bb49,0x3cf1bd62,0x3d183d4e,0xbd7b3c48,0x3c79bd78,0x3d463d22,0xbd673cdb,0xbd35bd35,0x3d71bcac,0xbbc93d7f,0xbd5cbd04,0x3d55bd0e,0x3c163d7d,0xbd75bc95,0x3d2cbd3e,
0xbc48bd7b,0x3d673cdb,0xbd623cf1,0x3c16bd7d,0xbcc43d6d,0xbd04bd5c,0x3d7f3bc9,0xbd2c3d3e,0x3d55bd0e,0xbb493d80,0xbd46bd22,0x3d78bc79,0xbd800000,0x3d18bd4e,0x3c953d75,0xbd71bcac,
0xbd0e3d55,0xbcacbd71,0x3d753c95,0xbd4e3d18,0x3d6dbcc4,0xbc793d78,0xbd22bd46,0x3d80bb49,0xbd7bbc48,0x3d3ebd2c,0x3bc93d7f,0xbd5cbd04,0x3d353d35,0xbd7d3c16,0x3cf1bd62,0x3cdb3d67,
0xbd35bd35,0x3d803b49,0xbd463d22,0x3c16bd7d,0x3d0e3d55,0xbd78bc79,0x3d62bcf1,0xbcac3d71,0xbcc4bd6d,0x3d673cdb,0xbd753c95,0x3d04bd5c,0x3c483d7b,0xbd4ebd18,0x3d7fbbc9,0xbd2c3d3e,
0xbd800000,0x3d3ebd2c,0xbbc93d7f,0xbd18bd4e,0x3d7b3c48,0xbd5c3d04,0x3c95bd75,0x3cdb3d67,0xbd6dbcc4,0x3d71bcac,0xbcf13d62,0xbc79bd78,0x3d553d0e,0xbd7d3c16,0x3d22bd46,0x3b493d80,
0x3c48bd7b,0x3cac3d71,0xbd46bd22,0x3d7d3c16,0x3d353d35,0xbd78bc79,0x3d75bc95,0xbd2c3d3e,0x3d553d0e,0xbd80bb49,0x3d62bcf1,0xbd043d5c,0xbd6d3cc4,0x3d18bd4e,0xbbc93d7f,0xbcdbbd67,
0x3d0e3d55,0xbd67bcdb,0x3d7fbbc9,0xbd4e3d18,0xbd800000,0x3d5cbd04,0xbcf13d62,0xbb49bd80,0xbd7b3c48,0x3d3ebd2c,0xbc953d75,0xbc79bd78,0x3cc4bd6d,0x3c163d7d,0xbd22bd46,0x3d713cac,
0x3cc43d6d,0xbd2cbd3e,0x3d623cf1,0xbd7dbc16,0x3d7bbc48,0xbd5c3d04,0x3d22bd46,0xbcac3d71,0xbd35bd35,0x3d673cdb,0xbd7fbbc9,0x3d78bc79,0xbd553d0e,0x3d18bd4e,0xbc953d75,0xbb49bd80,
0x3d6d3cc4,0xbd80bb49,0x3d75bc95,0xbd4e3d18,0x3d0ebd55,0xbc793d78,0xbbc9bd7f,0x3cdb3d67,0xbd800000,0x3d71bcac,0xbd463d22,0x3d04bd5c,0xbc483d7b,0xbc16bd7d,0x3cf13d62,0xbd3ebd2c,
0x3d0ebd55,0xbcdb3d67,0x3c95bd75,0xbc163d7d,0x3d6dbcc4,0xbd5c3d04,0x3d46bd22,0xbd2c3d3e,0x3d7b3c48,0xbd80bb49,0x3d7fbbc9,0xbd783c79,0x3d353d35,0xbd4ebd18,0x3d623cf1,0xbd71bcac,
0x3c483d7b,0xbcacbd71,0x3cf13d62,0xbd18bd4e,0xbcc43d6d,0x3c79bd78,0xbbc93d7f,0xbb49bd80,0xbd553d0e,0x3d3ebd2c,0xbd223d46,0x3d04bd5c,0xbd800000,0x3d7dbc16,0xbd753c95,0x3d67bcdb,
0x3d80,0x3b49bd80,0xbbc93d7f,0x3c16bd7d,0xbc483d7b,0x3c79bd78,0xbc953d75,0x3cacbd71,0xbcc43d6d,0x3cdbbd67,0xbcf13d62,0x3d04bd5c,0xbd0e3d55,0x3d18bd4e,0xbd223d46,0x3d2cbd3e,
0xbd353d35,0x3d3ebd2c,0xbd463d22,0x3d4ebd18,0xbd553d0e,0x3d5cbd04,0xbd623cf1,0x3d67bcdb,0xbd6d3cc4,0x3d71bcac,0xbd753c95,0x3d78bc79,0xbd7b3c48,0x3d7dbc16,0xbd7f3bc9,0x3d80bb49,
0xbd553d0e,0x3d71bcac,0xbd7f3bc9,0x3d7d3c16,0x3d80,0x3c79bd78,0xbcf13d62,0x3d2cbd3e,0xbc48bd7b,0xbb493d80,0x3c95bd75,0xbd043d5c,0xbd6dbcc4,0x3d4e3d18,0xbd22bd46,0x3cdb3d67,
0x3d7b3c48,0xbd67bcdb,0x3d463d22,0xbd18bd4e,0x3d35bd35,0xbd5c3d04,0x3d75bc95,0xbd803b49,0xbd0e3d55,0x3d3ebd2c,0xbd623cf1,0x3d78bc79,0x3cc43d6d,0xbc16bd7d,0xbbc93d7f,0x3cacbd71,
0x3cc4bd6d,0xbd3e3d2c,0x3d75bc95,0xbd7dbc16,0x3d553d0e,0xbd04bd5c,0x3bc93d7f,0x3cacbd71,0x3d80,0x3cdbbd67,0xbd463d22,0x3d78bc79,0xbd7bbc48,0x3d4e3d18,0xbcf1bd62,0x3b493d80,
0x3d6dbcc4,0xbd80bb49,0x3d623cf1,0xbd18bd4e,0x3c483d7b,0x3c79bd78,0xbd223d46,0x3d67bcdb,0xbd353d35,0x3d71bcac,0xbd7fbbc9,0x3d5c3d04,0xbd0ebd55,0x3c163d7d,0x3c95bd75,0xbd2c3d3e,
0xbd7b3c48,0x3d673cdb,0xbcf1bd62,0xbc163d7d,0x3d6d3cc4,0xbd04bd5c,0xbbc93d7f,0x3d2cbd3e,0xbd0ebd55,0xbb493d80,0x3d22bd46,0xbd783c79,0x3d80,0x3d18bd4e,0xbd753c95,0x3d713cac,
0x3d553d0e,0xbcacbd71,0xbc953d75,0x3d4ebd18,0xbcc4bd6d,0xbc793d78,0x3d46bd22,0xbd803b49,0xbc483d7b,0x3d3ebd2c,0xbd7f3bc9,0x3d5c3d04,0x3d35bd35,0xbd7d3c16,0x3d623cf1,0xbcdbbd67,
0xbd353d35,0x3d803b49,0xbd22bd46,0xbc163d7d,0x3d55bd0e,0xbd78bc79,0x3cf13d62,0x3cacbd71,0xbd6d3cc4,0x3d673cdb,0xbc95bd75,0xbd043d5c,0x3d7bbc48,0xbd4ebd18,0x3bc93d7f,0x3d2cbd3e,
0x3d80,0x3d3ebd2c,0xbd7fbbc9,0x3d183d4e,0x3c48bd7b,0xbd5c3d04,0x3d753c95,0xbcdbbd67,0xbcc43d6d,0x3d71bcac,0xbd62bcf1,0x3c793d78,0x3d0ebd55,0xbd7d3c16,0x3d463d22,0xbb49bd80,
0xbd7bbc48,0x3cac3d71,0x3d22bd46,0xbd7dbc16,0x3d35bd35,0xbd78bc79,0x3c953d75,0x3d2cbd3e,0x3d0ebd55,0xbd80bb49,0x3cf13d62,0x3d04bd5c,0x3cc43d6d,0x3d18bd4e,0xbd7fbbc9,0x3cdb3d67,
0x3d55bd0e,0xbd67bcdb,0x3bc93d7f,0x3d4ebd18,0x3d80,0x3d5cbd04,0xbd62bcf1,0x3b493d80,0x3c483d7b,0x3d3ebd2c,0xbd75bc95,0x3c793d78,0xbd6dbcc4,0x3c163d7d,0x3d46bd22,0xbd71bcac,
0x3d6dbcc4,0xbd2cbd3e,0xbcf13d62,0x3d7d3c16,0xbc48bd7b,0xbd5c3d04,0x3d463d22,0x3cacbd71,0xbd353d35,0x3d673cdb,0x3bc9bd7f,0xbd783c79,0x3d0e3d55,0x3d18bd4e,0xbd75bc95,0x3b493d80,
0x3cc4bd6d,0xbd80bb49,0x3c953d75,0x3d4ebd18,0xbd55bd0e,0xbc793d78,0x3d7fbbc9,0xbcdbbd67,0x3d80,0x3d71bcac,0xbd22bd46,0xbd043d5c,0x3d7b3c48,0xbc16bd7d,0xbd623cf1,0x3d3e3d2c,
0xbd55bd0e,0xbcdb3d67,0x3d753c95,0x3c16bd7d,0xbcc4bd6d,0xbd5c3d04,0x3d223d46,0x3d2cbd3e,0x3c48bd7b,0xbd80bb49,0x3bc93d7f,0x3d78bc79,0x3d35bd35,0xbd4ebd18,0xbcf13d62,0x3d713cac,
0x3d7bbc48,0xbcacbd71,0xbd623cf1,0x3d183d4e,0x3d6d3cc4,0x3c79bd78,0xbd7fbbc9,0x3b493d80,0x3d0e3d55,0x3d3ebd2c,0xbd46bd22,0xbd043d5c,0x3d80,0x3d7dbc16,0xbc95bd75,0xbd673cdb,
0xbd800000,0x3d803b49,0xbd7fbbc9,0x3d7d3c16,0xbd7bbc48,0x3d783c79,0xbd75bc95,0x3d713cac,0xbd6dbcc4,0x3d673cdb,0xbd62bcf1,0x3d5c3d04,0xbd55bd0e,0x3d4e3d18,0xbd46bd22,0x3d3e3d2c,
0xbd35bd35,0x3d2c3d3e,0xbd22bd46,0x3d183d4e,0xbd0ebd55,0x3d043d5c,0xbcf1bd62,0x3cdb3d67,0xbcc4bd6d,0x3cac3d71,0xbc95bd75,0x3c793d78,0xbc48bd7b,0x3c163d7d,0xbbc9bd7f,0x3b493d80,
0xbd0ebd55,0x3cac3d71,0xbbc9bd7f,0xbc163d7d,0xbd800000,0x3d783c79,0xbd62bcf1,0x3d3e3d2c,0x3d7bbc48,0xbd80bb49,0x3d753c95,0xbd5cbd04,0x3cc4bd6d,0xbd183d4e,0x3d46bd22,0xbd673cdb,
0xbc483d7b,0x3cdbbd67,0xbd223d46,0x3d4ebd18,0x3d353d35,0xbd04bd5c,0x3c953d75,0xbb49bd80,0xbd55bd0e,0x3d2c3d3e,0xbcf1bd62,0x3c793d78,0xbd6d3cc4,0x3d7dbc16,0xbd7fbbc9,0x3d713cac,
0x3d6d3cc4,0xbd2cbd3e,0x3c953d75,0x3c16bd7d,0xbd0e3d55,0x3d5cbd04,0xbd7f3bc9,0x3d713cac,0xbd800000,0x3d673cdb,0xbd22bd46,0x3c793d78,0x3c48bd7b,0xbd183d4e,0x3d62bcf1,0xbd803b49,
0x3cc43d6d,0x3b49bd80,0xbcf13d62,0x3d4ebd18,0xbd7b3c48,0x3d783c79,0xbd46bd22,0x3cdb3d67,0xbd35bd35,0x3cac3d71,0x3bc9bd7f,0xbd043d5c,0x3d55bd0e,0xbd7d3c16,0x3d753c95,0xbd3ebd2c,
0xbc48bd7b,0xbcdb3d67,0x3d62bcf1,0xbd7dbc16,0xbcc43d6d,0x3d5cbd04,0xbd7fbbc9,0x3d3e3d2c,0x3d55bd0e,0xbd80bb49,0x3d463d22,0xbc79bd78,0xbd800000,0x3d4e3d18,0xbc95bd75,0xbcac3d71,
0xbd0e3d55,0x3d71bcac,0xbd75bc95,0x3d183d4e,0x3d6dbcc4,0xbd78bc79,0x3d223d46,0xbb49bd80,0xbd7bbc48,0x3d2c3d3e,0xbbc9bd7f,0xbd043d5c,0x3d353d35,0xbc16bd7d,0xbcf13d62,0x3d67bcdb,
0xbd35bd35,0xbb493d80,0x3d46bd22,0xbd7dbc16,0x3d0e3d55,0x3c79bd78,0xbd623cf1,0x3d713cac,0xbcc4bd6d,0xbcdb3d67,0x3d75bc95,0xbd5cbd04,0x3c483d7b,0x3d18bd4e,0xbd7f3bc9,0x3d3e3d2c,
0xbd800000,0x3d2c3d3e,0x3bc9bd7f,0xbd4e3d18,0x3d7b3c48,0xbd04bd5c,0xbc953d75,0x3d67bcdb,0xbd6dbcc4,0x3cac3d71,0x3cf1bd62,0xbd783c79,0x3d553d0e,0xbc16bd7d,0xbd223d46,0x3d80bb49,
0x3c48bd7b,0xbd713cac,0x3d463d22,0x3c16bd7d,0x3d353d35,0x3c79bd78,0xbd753c95,0x3d3e3d2c,0x3d553d0e,0x3b49bd80,0xbd623cf1,0x3d5c3d04,0xbd6d3cc4,0x3d4e3d18,0x3bc9bd7f,0xbd673cdb,
0x3d0e3d55,0x3cdbbd67,0xbd7f3bc9,0x3d183d4e,0xbd800000,0x3d043d5c,0x3cf1bd62,0xbd803b49,0xbd7b3c48,0x3d2c3d3e,0x3c95bd75,0xbd783c79,0x3cc4bd6d,0xbd7d3c16,0x3d223d46,0x3cacbd71,
0x3cc43d6d,0x3d3ebd2c,0xbd62bcf1,0xbc163d7d,0x3d7bbc48,0xbd04bd5c,0xbd223d46,0x3d713cac,0xbd35bd35,0xbcdb3d67,0x3d7f3bc9,0xbc79bd78,0xbd553d0e,0x3d4e3d18,0x3c95bd75,0xbd803b49,
0x3d6d3cc4,0x3b49bd80,0xbd753c95,0x3d183d4e,0x3d0ebd55,0xbd78bc79,0x3bc93d7f,0x3d67bcdb,0xbd800000,0x3cac3d71,0x3d46bd22,0xbd5cbd04,0xbc483d7b,0x3d7dbc16,0xbcf1bd62,0xbd2c3d3e,
0x3d0ebd55,0xbd67bcdb,0xbc953d75,0x3d7d3c16,0x3d6dbcc4,0xbd04bd5c,0xbd463d22,0x3d3e3d2c,0x3d7b3c48,0x3b49bd80,0xbd7f3bc9,0x3c793d78,0x3d353d35,0x3d18bd4e,0xbd62bcf1,0xbcac3d71,
0x3c483d7b,0x3d71bcac,0xbcf1bd62,0xbd4e3d18,0xbcc43d6d,0x3d783c79,0x3bc9bd7f,0xbd803b49,0xbd553d0e,0x3d2c3d3e,0x3d22bd46,0xbd5cbd04,0xbd800000,0x3c163d7d,0x3d75bc95,0xbcdbbd67,
0x3d80,0x3d803b49,0x3bc9bd7f,0xbd7dbc16,0xbc483d7b,0x3d783c79,0x3c95bd75,0xbd71bcac,0xbcc43d6d,0x3d673cdb,0x3cf1bd62,0xbd5cbd04,0xbd0e3d55,0x3d4e3d18,0x3d22bd46,0xbd3ebd2c,
0xbd353d35,0x3d2c3d3e,0x3d46bd22,0xbd18bd4e,0xbd553d0e,0x3d043d5c,0x3d62bcf1,0xbcdbbd67,0xbd6d3cc4,0x3cac3d71,0x3d75bc95,0xbc79bd78,0xbd7b3c48,0x3c163d7d,0x3d7fbbc9,0xbb49bd80,
0xbd553d0e,0x3cac3d71,0x3d7fbbc9,0x3c16bd7d,0x3d80,0x3d783c79,0x3cf1bd62,0xbd3ebd2c,0xbc48bd7b,0xbd80bb49,0xbc953d75,0x3d5c3d04,0xbd6dbcc4,0xbd183d4e,0x3d223d46,0x3d67bcdb,
0x3d7b3c48,0x3cdbbd67,0xbd46bd22,0xbd4e3d18,0x3d35bd35,0xbd04bd5c,0xbd753c95,0x3b493d80,0xbd0e3d55,0x3d2c3d3e,0x3d62bcf1,0xbc79bd78,0x3cc43d6d,0x3d7dbc16,0x3bc9bd7f,0xbd71bcac,
0x3cc4bd6d,0xbd2cbd3e,0xbd753c95,0xbc163d7d,0x3d553d0e,0x3d5cbd04,0xbbc9bd7f,0xbd71bcac,0x3d80,0x3d673cdb,0x3d46bd22,0xbc79bd78,0xbd7bbc48,0xbd183d4e,0x3cf13d62,0x3d80bb49,
0x3d6dbcc4,0x3b49bd80,0xbd62bcf1,0xbd4e3d18,0x3c483d7b,0x3d783c79,0x3d22bd46,0xbcdbbd67,0xbd353d35,0x3cac3d71,0x3d7f3bc9,0x3d04bd5c,0xbd0ebd55,0xbd7d3c16,0xbc953d75,0x3d3e3d2c,
0xbd7b3c48,0xbcdb3d67,0x3cf13d62,0x3d7d3c16,0x3d6d3cc4,0x3d5cbd04,0x3bc9bd7f,0xbd3ebd2c,0xbd0ebd55,0xbd80bb49,0xbd223d46,0x3c793d78,0x3d80,0x3d4e3d18,0x3d75bc95,0x3cacbd71,
0x3d553d0e,0x3d71bcac,0x3c95bd75,0xbd18bd4e,0xbcc4bd6d,0xbd78bc79,0xbd463d22,0x3b493d80,0xbc483d7b,0x3d2c3d3e,0x3d7fbbc9,0x3d04bd5c,0x3d35bd35,0xbc16bd7d,0xbd62bcf1,0xbd673cdb,
0xbd353d35,0xbb493d80,0x3d223d46,0x3d7d3c16,0x3d55bd0e,0x3c79bd78,0xbcf1bd62,0xbd71bcac,0xbd6d3cc4,0xbcdb3d67,0x3c953d75,0x3d5c3d04,0x3d7bbc48,0x3d18bd4e,0xbbc9bd7f,0xbd3ebd2c,
0x3d80,0x3d2c3d3e,0x3d7f3bc9,0x3d4ebd18,0x3c48bd7b,0xbd04bd5c,0xbd75bc95,0xbd673cdb,0xbcc43d6d,0x3cac3d71,0x3d623cf1,0x3d78bc79,0x3d0ebd55,0xbc16bd7d,0xbd46bd22,0xbd803b49,
0xbd7bbc48,0xbd713cac,0xbd223d46,0xbc163d7d,0x3d35bd35,0x3c79bd78,0xbc95bd75,0xbd3ebd2c,0x3d0ebd55,0x3b49bd80,0xbcf1bd62,0xbd5cbd04,0x3cc43d6d,0x3d4e3d18,0x3d7f3bc9,0x3d67bcdb,
0x3d55bd0e,0x3cdbbd67,0xbbc9bd7f,0xbd18bd4e,0x3d80,0x3d043d5c,0x3d623cf1,0x3d80bb49,0x3c483d7b,0x3d2c3d3e,0x3d753c95,0x3d78bc79,0xbd6dbcc4,0xbd7d3c16,0xbd463d22,0xbcac3d71,
0x3d6dbcc4,0x3d3ebd2c,0x3cf1bd62,0x3c16bd7d,0xbc48bd7b,0xbd04bd5c,0xbd46bd22,0xbd71bcac,0xbd353d35,0xbcdb3d67,0xbbc93d7f,0x3c793d78,0x3d0e3d55,0x3d4e3d18,0x3d753c95,0x3d80bb49,
0x3cc4bd6d,0x3b49bd80,0xbc95bd75,0xbd18bd4e,0xbd55bd0e,0xbd78bc79,0xbd7f3bc9,0xbd673cdb,0x3d80,0x3cac3d71,0x3d223d46,0x3d5c3d04,0x3d7b3c48,0x3d7dbc16,0x3d62bcf1,0x3d2cbd3e,
0xbd55bd0e,0xbd67bcdb,0xbd75bc95,0xbd7dbc16,0xbcc4bd6d,0xbd04bd5c,0xbd22bd46,0xbd3ebd2c,0x3c48bd7b,0x3b49bd80,0xbbc9bd7f,0xbc79bd78,0x3d35bd35,0x3d18bd4e,0x3cf1bd62,0x3cacbd71,
0x3d7bbc48,0x3d71bcac,0x3d62bcf1,0x3d4ebd18,0x3d6d3cc4,0x3d783c79,0x3d7f3bc9,0x3d80bb49,0x3d0e3d55,0x3d2c3d3e,0x3d463d22,0x3d5c3d04,0x3d80,0x3c163d7d,0x3c953d75,0x3cdb3d67,
0xbd800000,0xbb493d80,0x3d7f3bc9,0x3c16bd7d,0xbd7bbc48,0xbc793d78,0x3d753c95,0x3cacbd71,0xbd6dbcc4,0xbcdb3d67,0x3d623cf1,0x3d04bd5c,0xbd55bd0e,0xbd183d4e,0x3d463d22,0x3d2cbd3e,
0xbd35bd35,0xbd3e3d2c,0x3d223d46,0x3d4ebd18,0xbd0ebd55,0xbd5c3d04,0x3cf13d62,0x3d67bcdb,0xbcc4bd6d,0xbd713cac,0x3c953d75,0x3d78bc79,0xbc48bd7b,0xbd7d3c16,0x3bc93d7f,0x3d80bb49,
0xbd0ebd55,0xbd713cac,0x3bc93d7f,0x3d7d3c16,0xbd800000,0xbc793d78,0x3d623cf1,0x3d2cbd3e,0x3d7bbc48,0x3b49bd80,0xbd75bc95,0xbd043d5c,0x3cc4bd6d,0xbd4ebd18,0xbd463d22,0x3cdb3d67,
0xbc483d7b,0x3d673cdb,0x3d22bd46,0xbd18bd4e,0x3d353d35,0x3d5cbd04,0xbc95bd75,0xbd803b49,0xbd55bd0e,0xbd3e3d2c,0x3cf13d62,0x3d78bc79,0xbd6d3cc4,0x3c163d7d,0x3d7f3bc9,0x3cacbd71,
0x3d6d3cc4,0x3d3ebd2c,0xbc95bd75,0xbd7dbc16,0xbd0e3d55,0x3d043d5c,0x3d7fbbc9,0x3cacbd71,0xbd800000,0xbcdb3d67,0x3d223d46,0x3d78bc79,0x3c48bd7b,0xbd4ebd18,0xbd623cf1,0x3b493d80,
0x3cc43d6d,0x3d803b49,0x3cf1bd62,0xbd18bd4e,0xbd7b3c48,0xbc793d78,0x3d463d22,0x3d67bcdb,0xbd35bd35,0xbd713cac,0xbbc93d7f,0x3d5c3d04,0x3d55bd0e,0xbc16bd7d,0xbd75bc95,0xbd2c3d3e,
0xbc48bd7b,0xbd67bcdb,0xbd623cf1,0xbc163d7d,0xbcc43d6d,0x3d043d5c,0x3d7f3bc9,0x3d2cbd3e,0x3d55bd0e,0x3b49bd80,0xbd46bd22,0xbd783c79,0xbd800000,0xbd183d4e,0x3c953d75,0x3d713cac,
0xbd0e3d55,0x3cac3d71,0x3d753c95,0x3d4ebd18,0x3d6dbcc4,0x3c79bd78,0xbd22bd46,0xbd803b49,0xbd7bbc48,0xbd3e3d2c,0x3bc93d7f,0x3d5c3d04,0x3d353d35,0x3d7dbc16,0x3cf1bd62,0xbcdbbd67,
0xbd35bd35,0xbd80bb49,0xbd463d22,0xbc163d7d,0x3d0e3d55,0x3d783c79,0x3d62bcf1,0x3cacbd71,0xbcc4bd6d,0xbd67bcdb,0xbd753c95,0xbd043d5c,0x3c483d7b,0x3d4e3d18,0x3d7fbbc9,0x3d2cbd3e,
0xbd800000,0xbd3e3d2c,0xbbc93d7f,0x3d183d4e,0x3d7b3c48,0x3d5cbd04,0x3c95bd75,0xbcdbbd67,0xbd6dbcc4,0xbd713cac,0xbcf13d62,0x3c793d78,0x3d553d0e,0x3d7dbc16,0x3d22bd46,0xbb49bd80,
0x3c48bd7b,0xbcacbd71,0xbd46bd22,0xbd7dbc16,0x3d353d35,0x3d783c79,0x3d75bc95,0x3d2cbd3e,0x3d553d0e,0x3d803b49,0x3d62bcf1,0x3d04bd5c,0xbd6d3cc4,0xbd183d4e,0xbbc93d7f,0x3cdb3d67,
0x3d0e3d55,0x3d673cdb,0x3d7fbbc9,0x3d4ebd18,0xbd800000,0xbd5c3d04,0xbcf13d62,0x3b493d80,0xbd7b3c48,0xbd3e3d2c,0xbc953d75,0x3c793d78,0x3cc4bd6d,0xbc16bd7d,0xbd22bd46,0xbd71bcac,
0x3cc43d6d,0x3d2c3d3e,0x3d623cf1,0x3d7d3c16,0x3d7bbc48,0x3d5cbd04,0x3d22bd46,0x3cacbd71,0xbd35bd35,0xbd67bcdb,0xbd7fbbc9,0xbd783c79,0xbd553d0e,0xbd183d4e,0xbc953d75,0x3b493d80,
0x3d6d3cc4,0x3d803b49,0x3d75bc95,0x3d4ebd18,0x3d0ebd55,0x3c79bd78,0xbbc9bd7f,0xbcdbbd67,0xbd800000,0xbd713cac,0xbd463d22,0xbd043d5c,0xbc483d7b,0x3c163d7d,0x3cf13d62,0x3d3e3d2c,
0x3d0ebd55,0x3cdbbd67,0x3c95bd75,0x3c16bd7d,0x3d6dbcc4,0x3d5cbd04,0x3d46bd22,0x3d2cbd3e,0x3d7b3c48,0x3d803b49,0x3d7fbbc9,0x3d78bc79,0x3d353d35,0x3d4e3d18,0x3d623cf1,0x3d713cac,
0x3c483d7b,0x3cac3d71,0x3cf13d62,0x3d183d4e,0xbcc43d6d,0xbc793d78,0xbbc93d7f,0x3b493d80,0xbd553d0e,0xbd3e3d2c,0xbd223d46,0xbd043d5c,0xbd800000,0xbd7d3c16,0xbd753c95,0xbd673cdb,
0x3d80,0xbbc93d7f,0xbc483d7b,0xbc953d75,0xbcc43d6d,0xbcf13d62,0xbd0e3d55,0xbd223d46,0xbd353d35,0xbd463d22,0xbd553d0e,0xbd623cf1,0xbd6d3cc4,0xbd753c95,0xbd7b3c48,0xbd7f3bc9,
0xbd800000,0xbd7fbbc9,0xbd7bbc48,0xbd75bc95,0xbd6dbcc4,0xbd62bcf1,0xbd55bd0e,0xbd46bd22,0xbd35bd35,0xbd22bd46,0xbd0ebd55,0xbcf1bd62,0xbcc4bd6d,0xbc95bd75,0xbc48bd7b,0xbbc9bd7f,
0xbd6d3cc4,0xbd7f3bc9,0xbd7bbc48,0xbd62bcf1,0x3d80,0xbc953d75,0xbd0e3d55,0xbd463d22,0x3cc4bd6d,0x3d22bd46,0x3d55bd0e,0x3d75bc95,0xbd35bd35,0xbcf1bd62,0xbc48bd7b,0x3bc9bd7f,
0x3cc43d6d,0x3bc93d7f,0xbc483d7b,0xbcf13d62,0x3d800000,0x3d753c95,0x3d553d0e,0x3d223d46,0xbd6dbcc4,0xbd46bd22,0xbd0ebd55,0xbc95bd75,0xbd353d35,0xbd623cf1,0xbd7b3c48,0xbd7fbbc9,
0x3d35bd35,0x3d75bc95,0x3d7b3c48,0x3d463d22,0x3cc43d6d,0xbbc93d7f,0xbd0e3d55,0xbd623cf1,0x3d80,0xbcf13d62,0xbd553d0e,0xbd7f3bc9,0xbd6dbcc4,0xbd22bd46,0xbc48bd7b,0x3c95bd75,
0x3d353d35,0x3c953d75,0xbc483d7b,0xbd223d46,0xbd6d3cc4,0xbd7fbbc9,0xbd55bd0e,0xbcf1bd62,0xbd800000,0xbd62bcf1,0xbd0ebd55,0xbbc9bd7f,0x3cc4bd6d,0x3d46bd22,0x3d7bbc48,0x3d753c95,
0xbd6dbcc4,0xbcf1bd62,0x3c48bd7b,0x3d46bd22,0x3d353d35,0x3bc93d7f,0xbd0e3d55,0xbd753c95,0xbcc4bd6d,0x3c95bd75,0x3d55bd0e,0x3d7f3bc9,0x3d80,0xbd223d46,0xbd7b3c48,0xbd62bcf1,
0xbcc43d6d,0xbd623cf1,0xbd7bbc48,0xbd22bd46,0x3d35bd35,0x3d7fbbc9,0x3d553d0e,0x3c953d75,0xbd6d3cc4,0xbd75bc95,0xbd0ebd55,0x3bc9bd7f,0x3d800000,0x3d463d22,0x3c483d7b,0xbcf13d62,
0xbd800000,0xbd22bd46,0x3c48bd7b,0x3d62bcf1,0x3d6d3cc4,0x3c953d75,0xbd0e3d55,0xbd7f3bc9,0xbd35bd35,0x3bc9bd7f,0x3d55bd0e,0x3d753c95,0x3cc43d6d,0xbcf13d62,0xbd7b3c48,0xbd46bd22,
0x3d80,0xbd463d22,0xbd7bbc48,0xbcf1bd62,0x3cc4bd6d,0x3d75bc95,0x3d553d0e,0x3bc93d7f,0xbd353d35,0xbd7fbbc9,0xbd0ebd55,0x3c95bd75,0x3d6dbcc4,0x3d623cf1,0x3c483d7b,0xbd223d46,
0xbcc4bd6d,0x3d22bd46,0x3d7b3c48,0x3c953d75,0x3d800000,0x3cf13d62,0xbd0e3d55,0xbd7fbbc9,0x3d6d3cc4,0x3bc93d7f,0xbd553d0e,0xbd62bcf1,0xbd353d35,0xbd75bc95,0xbc48bd7b,0x3d46bd22,
0x3d6dbcc4,0x3d463d22,0xbc483d7b,0xbd753c95,0x3d80,0xbd623cf1,0xbd55bd0e,0x3bc9bd7f,0xbcc43d6d,0xbd7f3bc9,0xbd0ebd55,0x3cf1bd62,0xbd35bd35,0x3c95bd75,0x3d7bbc48,0x3d223d46,
0x3d353d35,0xbcf13d62,0xbd7bbc48,0xbbc9bd7f,0x3d6dbcc4,0x3d223d46,0xbd0e3d55,0xbd75bc95,0xbd800000,0xbc95bd75,0x3d55bd0e,0x3d463d22,0xbcc43d6d,0xbd7fbbc9,0xbc48bd7b,0x3d62bcf1,
0x3d35bd35,0x3d623cf1,0xbc483d7b,0xbd7f3bc9,0xbcc4bd6d,0x3d46bd22,0x3d553d0e,0xbc953d75,0x3d80,0xbd753c95,0xbd0ebd55,0x3d22bd46,0x3d6d3cc4,0xbbc93d7f,0xbd7b3c48,0xbcf1bd62,
0x3cc4bd6d,0x3d753c95,0xbc483d7b,0xbd7fbbc9,0x3d35bd35,0x3d463d22,0xbd0e3d55,0xbd62bcf1,0x3d6dbcc4,0x3cf13d62,0xbd553d0e,0xbd22bd46,0x3d800000,0x3bc93d7f,0xbd7b3c48,0xbc95bd75,
0x3d6d3cc4,0xbc953d75,0xbd7bbc48,0x3bc9bd7f,0x3d353d35,0xbd223d46,0xbd55bd0e,0x3cf1bd62,0x3cc43d6d,0xbd623cf1,0xbd0ebd55,0x3d46bd22,0x3d80,0xbd7f3bc9,0xbc48bd7b,0x3d75bc95,
0xbd800000,0xbd7fbbc9,0xbd7bbc48,0xbd75bc95,0xbd6dbcc4,0xbd62bcf1,0xbd55bd0e,0xbd46bd22,0xbd35bd35,0xbd22bd46,0xbd0ebd55,0xbcf1bd62,0xbcc4bd6d,0xbc95bd75,0xbc48bd7b,0xbbc9bd7f,
0x8000bd80,0x3bc9bd7f,0x3c48bd7b,0x3c95bd75,0x3cc4bd6d,0x3cf1bd62,0x3d0ebd55,0x3d22bd46,0x3d35bd35,0x3d46bd22,0x3d55bd0e,0x3d62bcf1,0x3d6dbcc4,0x3d75bc95,0x3d7bbc48,0x3d7fbbc9,
0xbcc4bd6d,0xbbc9bd7f,0x3c48bd7b,0x3cf1bd62,0xbd800000,0xbd75bc95,0xbd55bd0e,0xbd22bd46,0x3d6d3cc4,0x3d463d22,0x3d0e3d55,0x3c953d75,0x3d35bd35,0x3d62bcf1,0x3d7bbc48,0x3d7f3bc9,
0xbd6d3cc4,0xbd7f3bc9,0xbd7bbc48,0xbd62bcf1,0x80003d80,0xbc953d75,0xbd0e3d55,0xbd463d22,0x3cc4bd6d,0x3d22bd46,0x3d55bd0e,0x3d75bc95,0xbd35bd35,0xbcf1bd62,0xbc48bd7b,0x3bc9bd7f,
0x3d353d35,0x3c953d75,0xbc483d7b,0xbd223d46,0xbd6d3cc4,0xbd7fbbc9,0xbd55bd0e,0xbcf1bd62,0xbd800000,0xbd62bcf1,0xbd0ebd55,0xbbc9bd7f,0x3cc4bd6d,0x3d46bd22,0x3d7bbc48,0x3d753c95,
0xbd353d35,0xbd753c95,0xbd7bbc48,0xbd46bd22,0xbcc4bd6d,0x3bc9bd7f,0x3d0ebd55,0x3d62bcf1,0x8000bd80,0x3cf1bd62,0x3d55bd0e,0x3d7fbbc9,0x3d6d3cc4,0x3d223d46,0x3c483d7b,0xbc953d75,
0x3cc4bd6d,0x3d62bcf1,0x3d7b3c48,0x3d223d46,0xbd353d35,0xbd7f3bc9,0xbd55bd0e,0xbc95bd75,0x3d6dbcc4,0x3d753c95,0x3d0e3d55,0xbbc93d7f,0xbd800000,0xbd46bd22,0xbc48bd7b,0x3cf1bd62,
0xbd6dbcc4,0xbcf1bd62,0x3c48bd7b,0x3d46bd22,0x3d353d35,0x3bc93d7f,0xbd0e3d55,0xbd753c95,0xbcc4bd6d,0x3c95bd75,0x3d55bd0e,0x3d7f3bc9,0x80003d80,0xbd223d46,0xbd7b3c48,0xbd62bcf1,
0x8000bd80,0x3d46bd22,0x3d7b3c48,0x3cf13d62,0xbcc43d6d,0xbd753c95,0xbd55bd0e,0xbbc9bd7f,0x3d35bd35,0x3d7f3bc9,0x3d0e3d55,0xbc953d75,0xbd6d3cc4,0xbd62bcf1,0xbc48bd7b,0x3d22bd46,
0xbd800000,0xbd22bd46,0x3c48bd7b,0x3d62bcf1,0x3d6d3cc4,0x3c953d75,0xbd0e3d55,0xbd7f3bc9,0xbd35bd35,0x3bc9bd7f,0x3d55bd0e,0x3d753c95,0x3cc43d6d,0xbcf13d62,0xbd7b3c48,0xbd46bd22,
0x3d6dbcc4,0x3d463d22,0xbc483d7b,0xbd753c95,0x80003d80,0xbd623cf1,0xbd55bd0e,0x3bc9bd7f,0xbcc43d6d,0xbd7f3bc9,0xbd0ebd55,0x3cf1bd62,0xbd35bd35,0x3c95bd75,0x3d7bbc48,0x3d223d46,
0x3cc43d6d,0xbd223d46,0xbd7bbc48,0xbc95bd75,0xbd800000,0xbcf1bd62,0x3d0ebd55,0x3d7f3bc9,0xbd6dbcc4,0xbbc9bd7f,0x3d55bd0e,0x3d623cf1,0x3d35bd35,0x3d753c95,0x3c483d7b,0xbd463d22,
0xbd353d35,0xbd62bcf1,0x3c48bd7b,0x3d7fbbc9,0x3cc43d6d,0xbd463d22,0xbd55bd0e,0x3c95bd75,0x8000bd80,0x3d75bc95,0x3d0e3d55,0xbd223d46,0xbd6dbcc4,0x3bc9bd7f,0x3d7bbc48,0x3cf13d62,
0x3d353d35,0xbcf13d62,0xbd7bbc48,0xbbc9bd7f,0x3d6dbcc4,0x3d223d46,0xbd0e3d55,0xbd75bc95,0xbd800000,0xbc95bd75,0x3d55bd0e,0x3d463d22,0xbcc43d6d,0xbd7fbbc9,0xbc48bd7b,0x3d62bcf1,
0x3d6d3cc4,0xbc953d75,0xbd7bbc48,0x3bc9bd7f,0x3d353d35,0xbd223d46,0xbd55bd0e,0x3cf1bd62,0x3cc43d6d,0xbd623cf1,0xbd0ebd55,0x3d46bd22,0x80003d80,0xbd7f3bc9,0xbc48bd7b,0x3d75bc95,
0xbcc43d6d,0xbd75bc95,0x3c48bd7b,0x3d7f3bc9,0xbd353d35,0xbd46bd22,0x3d0ebd55,0x3d623cf1,0xbd6d3cc4,0xbcf1bd62,0x3d55bd0e,0x3d223d46,0xbd800000,0xbbc9bd7f,0x3d7bbc48,0x3c953d75,
0x3d80,0xbd7fbbc9,0x3c48bd7b,0x3d753c95,0xbcc43d6d,0xbd62bcf1,0x3d0ebd55,0x3d463d22,0xbd353d35,0xbd22bd46,0x3d55bd0e,0x3cf13d62,0xbd6d3cc4,0xbc95bd75,0x3d7bbc48,0x3bc93d7f,
0xbd800000,0x3bc9bd7f,0x3d7b3c48,0xbc953d75,0xbd6dbcc4,0x3cf1bd62,0x3d553d0e,0xbd223d46,0xbd35bd35,0x3d46bd22,0x3d0e3d55,0xbd623cf1,0xbcc4bd6d,0x3d75bc95,0x3c483d7b,0xbd7f3bc9,
0xbd6d3cc4,0xbbc9bd7f,0x3d7b3c48,0xbcf13d62,0x3d80,0xbd75bc95,0x3d0ebd55,0x3d223d46,0x3cc4bd6d,0x3d463d22,0xbd553d0e,0xbc95bd75,0xbd35bd35,0x3d62bcf1,0x3c483d7b,0xbd7fbbc9,
0x3cc43d6d,0xbd7f3bc9,0x3c48bd7b,0x3d623cf1,0x3d800000,0xbc953d75,0xbd55bd0e,0x3d46bd22,0xbd6dbcc4,0x3d22bd46,0x3d0e3d55,0xbd753c95,0xbd353d35,0xbcf1bd62,0x3d7bbc48,0xbbc93d7f,
0x3d35bd35,0x3c953d75,0xbd7bbc48,0x3d22bd46,0x3cc43d6d,0xbd7fbbc9,0x3d0ebd55,0x3cf13d62,0x3d80,0xbd62bcf1,0x3d55bd0e,0x3bc93d7f,0xbd6dbcc4,0x3d46bd22,0x3c483d7b,0xbd75bc95,
0x3d353d35,0xbd753c95,0x3c48bd7b,0x3d463d22,0xbd6d3cc4,0x3bc9bd7f,0x3d553d0e,0xbd623cf1,0xbd800000,0x3cf1bd62,0x3d0e3d55,0xbd7f3bc9,0x3cc4bd6d,0x3d223d46,0xbd7b3c48,0x3c95bd75,
0xbd6dbcc4,0x3d62bcf1,0xbc483d7b,0xbd22bd46,0x3d353d35,0xbd7f3bc9,0x3d0ebd55,0x3c953d75,0xbcc4bd6d,0x3d753c95,0xbd553d0e,0x3bc9bd7f,0x3d80,0xbd46bd22,0x3d7bbc48,0xbcf13d62,
0xbcc43d6d,0xbcf1bd62,0x3d7b3c48,0xbd463d22,0x3d35bd35,0x3bc93d7f,0xbd55bd0e,0x3d75bc95,0xbd6d3cc4,0x3c95bd75,0x3d0e3d55,0xbd7fbbc9,0x3d800000,0xbd223d46,0xbc48bd7b,0x3d623cf1,
0xbd800000,0x3d46bd22,0xbc483d7b,0xbcf1bd62,0x3d6d3cc4,0xbd753c95,0x3d0ebd55,0x3bc93d7f,0xbd35bd35,0x3d7f3bc9,0xbd553d0e,0x3c95bd75,0x3cc43d6d,0xbd62bcf1,0x3d7bbc48,0xbd223d46,
0x3d80,0xbd22bd46,0x3d7b3c48,0xbd623cf1,0x3cc4bd6d,0x3c953d75,0xbd55bd0e,0x3d7fbbc9,0xbd353d35,0x3bc9bd7f,0x3d0e3d55,0xbd75bc95,0x3d6dbcc4,0xbcf13d62,0xbc48bd7b,0x3d463d22,
0xbcc4bd6d,0x3d463d22,0xbd7bbc48,0x3d75bc95,0x3d800000,0xbd623cf1,0x3d0ebd55,0xbbc93d7f,0x3d6d3cc4,0xbd7f3bc9,0x3d55bd0e,0xbcf13d62,0xbd353d35,0x3c95bd75,0x3c483d7b,0xbd22bd46,
0x3d6dbcc4,0xbd223d46,0x3c48bd7b,0x3c953d75,0x3d80,0xbcf1bd62,0x3d553d0e,0xbd7fbbc9,0xbcc43d6d,0xbbc9bd7f,0x3d0e3d55,0xbd62bcf1,0xbd35bd35,0x3d753c95,0xbd7b3c48,0x3d46bd22,
0x3d353d35,0xbd62bcf1,0x3d7b3c48,0xbd7f3bc9,0x3d6dbcc4,0xbd463d22,0x3d0ebd55,0xbc953d75,0xbd800000,0x3d75bc95,0xbd553d0e,0x3d22bd46,0xbcc43d6d,0x3bc9bd7f,0x3c483d7b,0xbcf1bd62,
0x3d35bd35,0xbcf13d62,0x3c48bd7b,0x3bc93d7f,0xbcc4bd6d,0x3d223d46,0xbd55bd0e,0x3d753c95,0x3d80,0xbc95bd75,0x3d0e3d55,0xbd46bd22,0x3d6d3cc4,0xbd7fbbc9,0x3d7bbc48,0xbd623cf1,
0x3cc4bd6d,0xbc953d75,0x3c48bd7b,0xbbc93d7f,0x3d35bd35,0xbd223d46,0x3d0ebd55,0xbcf13d62,0x3d6dbcc4,0xbd623cf1,0x3d55bd0e,0xbd463d22,0x3d800000,0xbd7f3bc9,0x3d7bbc48,0xbd753c95,
0x3d6d3cc4,0xbd75bc95,0x3d7b3c48,0xbd7fbbc9,0x3d353d35,0xbd46bd22,0x3d553d0e,0xbd62bcf1,0x3cc43d6d,0xbcf1bd62,0x3d0e3d55,0xbd22bd46,0x3d80,0xbbc9bd7f,0x3c483d7b,0xbc95bd75,
0xbd800000,0x3bc9bd7f,0x3d7b3c48,0xbc953d75,0xbd6dbcc4,0x3cf1bd62,0x3d553d0e,0xbd223d46,0xbd35bd35,0x3d46bd22,0x3d0e3d55,0xbd623cf1,0xbcc4bd6d,0x3d75bc95,0x3c483d7b,0xbd7f3bc9,
0x8000bd80,0x3d7f3bc9,0xbc483d7b,0xbd75bc95,0x3cc4bd6d,0x3d623cf1,0xbd0e3d55,0xbd46bd22,0x3d35bd35,0x3d223d46,0xbd553d0e,0xbcf1bd62,0x3d6dbcc4,0x3c953d75,0xbd7b3c48,0xbbc9bd7f,
0xbcc4bd6d,0x3d7fbbc9,0xbc483d7b,0xbd62bcf1,0xbd800000,0x3c95bd75,0x3d553d0e,0xbd463d22,0x3d6d3cc4,0xbd223d46,0xbd0ebd55,0x3d75bc95,0x3d35bd35,0x3cf13d62,0xbd7b3c48,0x3bc9bd7f,
0xbd6d3cc4,0xbbc9bd7f,0x3d7b3c48,0xbcf13d62,0x80003d80,0xbd75bc95,0x3d0ebd55,0x3d223d46,0x3cc4bd6d,0x3d463d22,0xbd553d0e,0xbc95bd75,0xbd35bd35,0x3d62bcf1,0x3c483d7b,0xbd7fbbc9,
0x3d353d35,0xbd753c95,0x3c48bd7b,0x3d463d22,0xbd6d3cc4,0x3bc9bd7f,0x3d553d0e,0xbd623cf1,0xbd800000,0x3cf1bd62,0x3d0e3d55,0xbd7f3bc9,0x3cc4bd6d,0x3d223d46,0xbd7b3c48,0x3c95bd75,
0xbd353d35,0xbc95bd75,0x3d7b3c48,0xbd223d46,0xbcc4bd6d,0x3d7f3bc9,0xbd0e3d55,0xbcf1bd62,0x8000bd80,0x3d623cf1,0xbd553d0e,0xbbc9bd7f,0x3d6d3cc4,0xbd463d22,0xbc48bd7b,0x3d753c95,
0x3cc4bd6d,0x3cf13d62,0xbd7bbc48,0x3d46bd22,0xbd353d35,0xbbc9bd7f,0x3d553d0e,0xbd753c95,0x3d6dbcc4,0xbc953d75,0xbd0ebd55,0x3d7f3bc9,0xbd800000,0x3d22bd46,0x3c483d7b,0xbd62bcf1,
0xbd6dbcc4,0x3d62bcf1,0xbc483d7b,0xbd22bd46,0x3d353d35,0xbd7f3bc9,0x3d0ebd55,0x3c953d75,0xbcc4bd6d,0x3d753c95,0xbd553d0e,0x3bc9bd7f,0x80003d80,0xbd46bd22,0x3d7bbc48,0xbcf13d62,
0x8000bd80,0x3d223d46,0xbd7bbc48,0x3d62bcf1,0xbcc43d6d,0xbc95bd75,0x3d553d0e,0xbd7f3bc9,0x3d35bd35,0xbbc93d7f,0xbd0ebd55,0x3d753c95,0xbd6d3cc4,0x3cf1bd62,0x3c483d7b,0xbd46bd22,
0xbd800000,0x3d46bd22,0xbc483d7b,0xbcf1bd62,0x3d6d3cc4,0xbd753c95,0x3d0ebd55,0x3bc93d7f,0xbd35bd35,0x3d7f3bc9,0xbd553d0e,0x3c95bd75,0x3cc43d6d,0xbd62bcf1,0x3d7bbc48,0xbd223d46,
0x3d6dbcc4,0xbd223d46,0x3c48bd7b,0x3c953d75,0x80003d80,0xbcf1bd62,0x3d553d0e,0xbd7fbbc9,0xbcc43d6d,0xbbc9bd7f,0x3d0e3d55,0xbd62bcf1,0xbd35bd35,0x3d753c95,0xbd7b3c48,0x3d46bd22,
0x3cc43d6d,0xbd46bd22,0x3d7b3c48,0xbd753c95,0xbd800000,0x3d62bcf1,0xbd0e3d55,0x3bc9bd7f,0xbd6dbcc4,0x3d7fbbc9,0xbd553d0e,0x3cf1bd62,0x3d35bd35,0xbc953d75,0xbc48bd7b,0x3d223d46,
0xbd353d35,0x3cf1bd62,0xbc483d7b,0xbbc9bd7f,0x3cc43d6d,0xbd22bd46,0x3d553d0e,0xbd75bc95,0x8000bd80,0x3c953d75,0xbd0ebd55,0x3d463d22,0xbd6dbcc4,0x3d7f3bc9,0xbd7b3c48,0x3d62bcf1,
0x3d353d35,0xbd62bcf1,0x3d7b3c48,0xbd7f3bc9,0x3d6dbcc4,0xbd463d22,0x3d0ebd55,0xbc953d75,0xbd800000,0x3d75bc95,0xbd553d0e,0x3d22bd46,0xbcc43d6d,0x3bc9bd7f,0x3c483d7b,0xbcf1bd62,
0x3d6d3cc4,0xbd75bc95,0x3d7b3c48,0xbd7fbbc9,0x3d353d35,0xbd46bd22,0x3d553d0e,0xbd62bcf1,0x3cc43d6d,0xbcf1bd62,0x3d0e3d55,0xbd22bd46,0x80003d80,0xbbc9bd7f,0x3c483d7b,0xbc95bd75,
0xbcc43d6d,0x3c95bd75,0xbc483d7b,0x3bc9bd7f,0xbd353d35,0x3d22bd46,0xbd0e3d55,0x3cf1bd62,0xbd6d3cc4,0x3d62bcf1,0xbd553d0e,0x3d46bd22,0xbd800000,0x3d7fbbc9,0xbd7b3c48,0x3d75bc95,
0x3d80,0x3bc9bd7f,0xbc483d7b,0x3c95bd75,0xbcc43d6d,0x3cf1bd62,0xbd0e3d55,0x3d22bd46,0xbd353d35,0x3d46bd22,0xbd553d0e,0x3d62bcf1,0xbd6d3cc4,0x3d75bc95,0xbd7b3c48,0x3d7fbbc9,
0xbd800000,0x3d7f3bc9,0xbd7bbc48,0x3d753c95,0xbd6dbcc4,0x3d623cf1,0xbd55bd0e,0x3d463d22,0xbd35bd35,0x3d223d46,0xbd0ebd55,0x3cf13d62,0xbcc4bd6d,0x3c953d75,0xbc48bd7b,0x3bc93d7f,
0xbd6d3cc4,0x3d7fbbc9,0xbd7bbc48,0x3d623cf1,0x3d80,0x3c95bd75,0xbd0e3d55,0x3d46bd22,0x3cc4bd6d,0xbd223d46,0x3d55bd0e,0xbd753c95,0xbd35bd35,0x3cf13d62,0xbc48bd7b,0xbbc93d7f,
0x3cc43d6d,0xbbc9bd7f,0xbc483d7b,0x3cf1bd62,0x3d800000,0xbd75bc95,0x3d553d0e,0xbd22bd46,0xbd6dbcc4,0x3d463d22,0xbd0ebd55,0x3c953d75,0xbd353d35,0x3d62bcf1,0xbd7b3c48,0x3d7f3bc9,
0x3d35bd35,0xbd753c95,0x3d7b3c48,0xbd46bd22,0x3cc43d6d,0x3bc9bd7f,0xbd0e3d55,0x3d62bcf1,0x3d80,0x3cf1bd62,0xbd553d0e,0x3d7fbbc9,0xbd6dbcc4,0x3d223d46,0xbc48bd7b,0xbc953d75,
0x3d353d35,0xbc95bd75,0xbc483d7b,0x3d22bd46,0xbd6d3cc4,0x3d7f3bc9,0xbd55bd0e,0x3cf13d62,0xbd800000,0x3d623cf1,0xbd0ebd55,0x3bc93d7f,0x3cc4bd6d,0xbd463d22,0x3d7bbc48,0xbd75bc95,
0xbd6dbcc4,0x3cf13d62,0x3c48bd7b,0xbd463d22,0x3d353d35,0xbbc9bd7f,0xbd0e3d55,0x3d75bc95,0xbcc4bd6d,0xbc953d75,0x3d55bd0e,0xbd7fbbc9,0x3d80,0x3d22bd46,0xbd7b3c48,0x3d623cf1,
0xbcc43d6d,0x3d62bcf1,0xbd7bbc48,0x3d223d46,0x3d35bd35,0xbd7f3bc9,0x3d553d0e,0xbc95bd75,0xbd6d3cc4,0x3d753c95,0xbd0ebd55,0xbbc93d7f,0x3d800000,0xbd46bd22,0x3c483d7b,0x3cf1bd62,
0xbd800000,0x3d223d46,0x3c48bd7b,0xbd623cf1,0x3d6d3cc4,0xbc95bd75,0xbd0e3d55,0x3d7fbbc9,0xbd35bd35,0xbbc93d7f,0x3d55bd0e,0xbd75bc95,0x3cc43d6d,0x3cf1bd62,0xbd7b3c48,0x3d463d22,
0x3d80,0x3d46bd22,0xbd7bbc48,0x3cf13d62,0x3cc4bd6d,0xbd753c95,0x3d553d0e,0xbbc9bd7f,0xbd353d35,0x3d7f3bc9,0xbd0ebd55,0xbc953d75,0x3d6dbcc4,0xbd62bcf1,0x3c483d7b,0x3d22bd46,
0xbcc4bd6d,0xbd223d46,0x3d7b3c48,0xbc95bd75,0x3d800000,0xbcf1bd62,0xbd0e3d55,0x3d7f3bc9,0x3d6d3cc4,0xbbc9bd7f,0xbd553d0e,0x3d623cf1,0xbd353d35,0x3d753c95,0xbc48bd7b,0xbd463d22,
0x3d6dbcc4,0xbd46bd22,0xbc483d7b,0x3d75bc95,0x3d80,0x3d62bcf1,0xbd55bd0e,0xbbc93d7f,0xbcc43d6d,0x3d7fbbc9,0xbd0ebd55,0xbcf13d62,0xbd35bd35,0xbc953d75,0x3d7bbc48,0xbd22bd46,
0x3d353d35,0x3cf1bd62,0xbd7bbc48,0x3bc93d7f,0x3d6dbcc4,0xbd22bd46,0xbd0e3d55,0x3d753c95,0xbd800000,0x3c953d75,0x3d55bd0e,0xbd46bd22,0xbcc43d6d,0x3d7f3bc9,0xbc48bd7b,0xbd623cf1,
0x3d35bd35,0xbd62bcf1,0xbc483d7b,0x3d7fbbc9,0xbcc4bd6d,0xbd463d22,0x3d553d0e,0x3c95bd75,0x3d80,0x3d75bc95,0xbd0ebd55,0xbd223d46,0x3d6d3cc4,0x3bc9bd7f,0xbd7b3c48,0x3cf13d62,
0x3cc4bd6d,0xbd75bc95,0xbc483d7b,0x3d7f3bc9,0x3d35bd35,0xbd46bd22,0xbd0e3d55,0x3d623cf1,0x3d6dbcc4,0xbcf1bd62,0xbd553d0e,0x3d223d46,0x3d800000,0xbbc9bd7f,0xbd7b3c48,0x3c953d75,
0x3d6d3cc4,0x3c95bd75,0xbd7bbc48,0xbbc93d7f,0x3d353d35,0x3d22bd46,0xbd55bd0e,0xbcf13d62,0x3cc43d6d,0x3d62bcf1,0xbd0ebd55,0xbd463d22,0x3d80,0x3d7fbbc9,0xbc48bd7b,0xbd753c95,
0xbd800000,0x3d7f3bc9,0xbd7bbc48,0x3d753c95,0xbd6dbcc4,0x3d623cf1,0xbd55bd0e,0x3d463d22,0xbd35bd35,0x3d223d46,0xbd0ebd55,0x3cf13d62,0xbcc4bd6d,0x3c953d75,0xbc48bd7b,0x3bc93d7f,
0x8000bd80,0xbbc93d7f,0x3c48bd7b,0xbc953d75,0x3cc4bd6d,0xbcf13d62,0x3d0ebd55,0xbd223d46,0x3d35bd35,0xbd463d22,0x3d55bd0e,0xbd623cf1,0x3d6dbcc4,0xbd753c95,0x3d7bbc48,0xbd7f3bc9,
0xbcc4bd6d,0x3bc93d7f,0x3c48bd7b,0xbcf13d62,0xbd800000,0x3d753c95,0xbd55bd0e,0x3d223d46,0x3d6d3cc4,0xbd46bd22,0x3d0e3d55,0xbc95bd75,0x3d35bd35,0xbd623cf1,0x3d7bbc48,0xbd7fbbc9,
0xbd6d3cc4,0x3d7fbbc9,0xbd7bbc48,0x3d623cf1,0x80003d80,0x3c95bd75,0xbd0e3d55,0x3d46bd22,0x3cc4bd6d,0xbd223d46,0x3d55bd0e,0xbd753c95,0xbd35bd35,0x3cf13d62,0xbc48bd7b,0xbbc93d7f,
0x3d353d35,0xbc95bd75,0xbc483d7b,0x3d22bd46,0xbd6d3cc4,0x3d7f3bc9,0xbd55bd0e,0x3cf13d62,0xbd800000,0x3d623cf1,0xbd0ebd55,0x3bc93d7f,0x3cc4bd6d,0xbd463d22,0x3d7bbc48,0xbd75bc95,
0xbd353d35,0x3d75bc95,0xbd7bbc48,0x3d463d22,0xbcc4bd6d,0xbbc93d7f,0x3d0ebd55,0xbd623cf1,0x8000bd80,0xbcf13d62,0x3d55bd0e,0xbd7f3bc9,0x3d6d3cc4,0xbd22bd46,0x3c483d7b,0x3c95bd75,
0x3cc4bd6d,0xbd623cf1,0x3d7b3c48,0xbd22bd46,0xbd353d35,0x3d7fbbc9,0xbd55bd0e,0x3c953d75,0x3d6dbcc4,0xbd75bc95,0x3d0e3d55,0x3bc9bd7f,0xbd800000,0x3d463d22,0xbc48bd7b,0xbcf13d62,
0xbd6dbcc4,0x3cf13d62,0x3c48bd7b,0xbd463d22,0x3d353d35,0xbbc9bd7f,0xbd0e3d55,0x3d75bc95,0xbcc4bd6d,0xbc953d75,0x3d55bd0e,0xbd7fbbc9,0x80003d80,0x3d22bd46,0xbd7b3c48,0x3d623cf1,
0x8000bd80,0xbd463d22,0x3d7b3c48,0xbcf1bd62,0xbcc43d6d,0x3d75bc95,0xbd55bd0e,0x3bc93d7f,0x3d35bd35,0xbd7fbbc9,0x3d0e3d55,0x3c95bd75,0xbd6d3cc4,0x3d623cf1,0xbc48bd7b,0xbd223d46,
0xbd800000,0x3d223d46,0x3c48bd7b,0xbd623cf1,0x3d6d3cc4,0xbc95bd75,0xbd0e3d55,0x3d7fbbc9,0xbd35bd35,0xbbc93d7f,0x3d55bd0e,0xbd75bc95,0x3cc43d6d,0x3cf1bd62,0xbd7b3c48,0x3d463d22,
0x3d6dbcc4,0xbd46bd22,0xbc483d7b,0x3d75bc95,0x80003d80,0x3d62bcf1,0xbd55bd0e,0xbbc93d7f,0xbcc43d6d,0x3d7fbbc9,0xbd0ebd55,0xbcf13d62,0xbd35bd35,0xbc953d75,0x3d7bbc48,0xbd22bd46,
0x3cc43d6d,0x3d22bd46,0xbd7bbc48,0x3c953d75,0xbd800000,0x3cf13d62,0x3d0ebd55,0xbd7fbbc9,0xbd6dbcc4,0x3bc93d7f,0x3d55bd0e,0xbd62bcf1,0x3d35bd35,0xbd75bc95,0x3c483d7b,0x3d46bd22,
0xbd353d35,0x3d623cf1,0x3c48bd7b,0xbd7f3bc9,0x3cc43d6d,0x3d46bd22,0xbd55bd0e,0xbc953d75,0x8000bd80,0xbd753c95,0x3d0e3d55,0x3d22bd46,0xbd6dbcc4,0xbbc93d7f,0x3d7bbc48,0xbcf1bd62,
0x3d353d35,0x3cf1bd62,0xbd7bbc48,0x3bc93d7f,0x3d6dbcc4,0xbd22bd46,0xbd0e3d55,0x3d753c95,0xbd800000,0x3c953d75,0x3d55bd0e,0xbd46bd22,0xbcc43d6d,0x3d7f3bc9,0xbc48bd7b,0xbd623cf1,
0x3d6d3cc4,0x3c95bd75,0xbd7bbc48,0xbbc93d7f,0x3d353d35,0x3d22bd46,0xbd55bd0e,0xbcf13d62,0x3cc43d6d,0x3d62bcf1,0xbd0ebd55,0xbd463d22,0x80003d80,0x3d7fbbc9,0xbc48bd7b,0xbd753c95,
0xbcc43d6d,0x3d753c95,0x3c48bd7b,0xbd7fbbc9,0xbd353d35,0x3d463d22,0x3d0ebd55,0xbd62bcf1,0xbd6d3cc4,0x3cf13d62,0x3d55bd0e,0xbd22bd46,0xbd800000,0x3bc93d7f,0x3d7bbc48,0xbc95bd75,
0x3d80,0x3d7f3bc9,0x3c48bd7b,0xbd75bc95,0xbcc43d6d,0x3d623cf1,0x3d0ebd55,0xbd46bd22,0xbd353d35,0x3d223d46,0x3d55bd0e,0xbcf1bd62,0xbd6d3cc4,0x3c953d75,0x3d7bbc48,0xbbc9bd7f,
0xbd800000,0xbbc93d7f,0x3d7b3c48,0x3c95bd75,0xbd6dbcc4,0xbcf13d62,0x3d553d0e,0x3d22bd46,0xbd35bd35,0xbd463d22,0x3d0e3d55,0x3d62bcf1,0xbcc4bd6d,0xbd753c95,0x3c483d7b,0x3d7fbbc9,
0xbd6d3cc4,0x3bc93d7f,0x3d7b3c48,0x3cf1bd62,0x3d80,0x3d753c95,0x3d0ebd55,0xbd22bd46,0x3cc4bd6d,0xbd46bd22,0xbd553d0e,0x3c953d75,0xbd35bd35,0xbd623cf1,0x3c483d7b,0x3d7f3bc9,
0x3cc43d6d,0x3d7fbbc9,0x3c48bd7b,0xbd62bcf1,0x3d800000,0x3c95bd75,0xbd55bd0e,0xbd463d22,0xbd6dbcc4,0xbd223d46,0x3d0e3d55,0x3d75bc95,0xbd353d35,0x3cf13d62,0x3d7bbc48,0x3bc9bd7f,
0x3d35bd35,0xbc95bd75,0xbd7bbc48,0xbd223d46,0x3cc43d6d,0x3d7f3bc9,0x3d0ebd55,0xbcf1bd62,0x3d80,0x3d623cf1,0x3d55bd0e,0xbbc9bd7f,0xbd6dbcc4,0xbd463d22,0x3c483d7b,0x3d753c95,
0x3d353d35,0x3d75bc95,0x3c48bd7b,0xbd46bd22,0xbd6d3cc4,0xbbc93d7f,0x3d553d0e,0x3d62bcf1,0xbd800000,0xbcf13d62,0x3d0e3d55,0x3d7fbbc9,0x3cc4bd6d,0xbd22bd46,0xbd7b3c48,0xbc953d75,
0xbd6dbcc4,0xbd623cf1,0xbc483d7b,0x3d223d46,0x3d353d35,0x3d7fbbc9,0x3d0ebd55,0xbc95bd75,0xbcc4bd6d,0xbd75bc95,0xbd553d0e,0xbbc93d7f,0x3d80,0x3d463d22,0x3d7bbc48,0x3cf1bd62,
0xbcc43d6d,0x3cf13d62,0x3d7b3c48,0x3d46bd22,0x3d35bd35,0xbbc9bd7f,0xbd55bd0e,0xbd753c95,0xbd6d3cc4,0xbc953d75,0x3d0e3d55,0x3d7f3bc9,0x3d800000,0x3d22bd46,0xbc48bd7b,0xbd62bcf1,
0xbd800000,0xbd463d22,0xbc483d7b,0x3cf13d62,0x3d6d3cc4,0x3d75bc95,0x3d0ebd55,0xbbc9bd7f,0xbd35bd35,0xbd7fbbc9,0xbd553d0e,0xbc953d75,0x3cc43d6d,0x3d623cf1,0x3d7bbc48,0x3d22bd46,
0x3d80,0x3d223d46,0x3d7b3c48,0x3d62bcf1,0x3cc4bd6d,0xbc95bd75,0xbd55bd0e,0xbd7f3bc9,0xbd353d35,0xbbc93d7f,0x3d0e3d55,0x3d753c95,0x3d6dbcc4,0x3cf1bd62,0xbc48bd7b,0xbd46bd22,
0xbcc4bd6d,0xbd46bd22,0xbd7bbc48,0xbd753c95,0x3d800000,0x3d62bcf1,0x3d0ebd55,0x3bc9bd7f,0x3d6d3cc4,0x3d7fbbc9,0x3d55bd0e,0x3cf1bd62,0xbd353d35,0xbc953d75,0x3c483d7b,0x3d223d46,
0x3d6dbcc4,0x3d22bd46,0x3c48bd7b,0xbc95bd75,0x3d80,0x3cf13d62,0x3d553d0e,0x3d7f3bc9,0xbcc43d6d,0x3bc93d7f,0x3d0e3d55,0x3d623cf1,0xbd35bd35,0xbd75bc95,0xbd7b3c48,0xbd463d22,
0x3d353d35,0x3d623cf1,0x3d7b3c48,0x3d7fbbc9,0x3d6dbcc4,0x3d46bd22,0x3d0ebd55,0x3c95bd75,0xbd800000,0xbd753c95,0xbd553d0e,0xbd223d46,0xbcc43d6d,0xbbc93d7f,0x3c483d7b,0x3cf13d62,
0x3d35bd35,0x3cf1bd62,0x3c48bd7b,0xbbc9bd7f,0xbcc4bd6d,0xbd22bd46,0xbd55bd0e,0xbd75bc95,0x3d80,0x3c953d75,0x3d0e3d55,0x3d463d22,0x3d6d3cc4,0x3d7f3bc9,0x3d7bbc48,0x3d62bcf1,
0x3cc4bd6d,0x3c95bd75,0x3c48bd7b,0x3bc9bd7f,0x3d35bd35,0x3d22bd46,0x3d0ebd55,0x3cf1bd62,0x3d6dbcc4,0x3d62bcf1,0x3d55bd0e,0x3d46bd22,0x3d800000,0x3d7fbbc9,0x3d7bbc48,0x3d75bc95,
0x3d6d3cc4,0x3d753c95,0x3d7b3c48,0x3d7f3bc9,0x3d353d35,0x3d463d22,0x3d553d0e,0x3d623cf1,0x3cc43d6d,0x3cf13d62,0x3d0e3d55,0x3d223d46,0x3d80,0x3bc93d7f,0x3c483d7b,0x3c953d75,
0xbd800000,0xbbc93d7f,0x3d7b3c48,0x3c95bd75,0xbd6dbcc4,0xbcf13d62,0x3d553d0e,0x3d22bd46,0xbd35bd35,0xbd463d22,0x3d0e3d55,0x3d62bcf1,0xbcc4bd6d,0xbd753c95,0x3c483d7b,0x3d7fbbc9,
0x8000bd80,0xbd7fbbc9,0xbc483d7b,0x3d753c95,0x3cc4bd6d,0xbd62bcf1,0xbd0e3d55,0x3d463d22,0x3d35bd35,0xbd22bd46,0xbd553d0e,0x3cf13d62,0x3d6dbcc4,0xbc95bd75,0xbd7b3c48,0x3bc93d7f,
0xbcc4bd6d,0xbd7f3bc9,0xbc483d7b,0x3d623cf1,0xbd800000,0xbc953d75,0x3d553d0e,0x3d46bd22,0x3d6d3cc4,0x3d22bd46,0xbd0ebd55,0xbd753c95,0x3d35bd35,0xbcf1bd62,0xbd7b3c48,0xbbc93d7f,
0xbd6d3cc4,0x3bc93d7f,0x3d7b3c48,0x3cf1bd62,0x80003d80,0x3d753c95,0x3d0ebd55,0xbd22bd46,0x3cc4bd6d,0xbd46bd22,0xbd553d0e,0x3c953d75,0xbd35bd35,0xbd623cf1,0x3c483d7b,0x3d7f3bc9,
0x3d353d35,0x3d75bc95,0x3c48bd7b,0xbd46bd22,0xbd6d3cc4,0xbbc93d7f,0x3d553d0e,0x3d62bcf1,0xbd800000,0xbcf13d62,0x3d0e3d55,0x3d7fbbc9,0x3cc4bd6d,0xbd22bd46,0xbd7b3c48,0xbc953d75,
0xbd353d35,0x3c953d75,0x3d7b3c48,0x3d22bd46,0xbcc4bd6d,0xbd7fbbc9,0xbd0e3d55,0x3cf13d62,0x8000bd80,0xbd62bcf1,0xbd553d0e,0x3bc93d7f,0x3d6d3cc4,0x3d46bd22,0xbc48bd7b,0xbd75bc95,
0x3cc4bd6d,0xbcf1bd62,0xbd7bbc48,0xbd463d22,0xbd353d35,0x3bc93d7f,0x3d553d0e,0x3d75bc95,0x3d6dbcc4,0x3c95bd75,0xbd0ebd55,0xbd7fbbc9,0xbd800000,0xbd223d46,0x3c483d7b,0x3d623cf1,
0xbd6dbcc4,0xbd623cf1,0xbc483d7b,0x3d223d46,0x3d353d35,0x3d7fbbc9,0x3d0ebd55,0xbc95bd75,0xbcc4bd6d,0xbd75bc95,0xbd553d0e,0xbbc93d7f,0x80003d80,0x3d463d22,0x3d7bbc48,0x3cf1bd62,
0x8000bd80,0xbd22bd46,0xbd7bbc48,0xbd623cf1,0xbcc43d6d,0x3c953d75,0x3d553d0e,0x3d7fbbc9,0x3d35bd35,0x3bc9bd7f,0xbd0ebd55,0xbd75bc95,0xbd6d3cc4,0xbcf13d62,0x3c483d7b,0x3d463d22,
0xbd800000,0xbd463d22,0xbc483d7b,0x3cf13d62,0x3d6d3cc4,0x3d75bc95,0x3d0ebd55,0xbbc9bd7f,0xbd35bd35,0xbd7fbbc9,0xbd553d0e,0xbc953d75,0x3cc43d6d,0x3d623cf1,0x3d7bbc48,0x3d22bd46,
0x3d6dbcc4,0x3d22bd46,0x3c48bd7b,0xbc95bd75,0x80003d80,0x3cf13d62,0x3d553d0e,0x3d7f3bc9,0xbcc43d6d,0x3bc93d7f,0x3d0e3d55,0x3d623cf1,0xbd35bd35,0xbd75bc95,0xbd7b3c48,0xbd463d22,
0x3cc43d6d,0x3d463d22,0x3d7b3c48,0x3d75bc95,0xbd800000,0xbd623cf1,0xbd0e3d55,0xbbc93d7f,0xbd6dbcc4,0xbd7f3bc9,0xbd553d0e,0xbcf13d62,0x3d35bd35,0x3c95bd75,0xbc48bd7b,0xbd22bd46,
0xbd353d35,0xbcf13d62,0xbc483d7b,0x3bc93d7f,0x3cc43d6d,0x3d223d46,0x3d553d0e,0x3d753c95,0x8000bd80,0xbc95bd75,0xbd0ebd55,0xbd46bd22,0xbd6dbcc4,0xbd7fbbc9,0xbd7b3c48,0xbd623cf1,
0x3d353d35,0x3d623cf1,0x3d7b3c48,0x3d7fbbc9,0x3d6dbcc4,0x3d46bd22,0x3d0ebd55,0x3c95bd75,0xbd800000,0xbd753c95,0xbd553d0e,0xbd223d46,0xbcc43d6d,0xbbc93d7f,0x3c483d7b,0x3cf13d62,
0x3d6d3cc4,0x3d753c95,0x3d7b3c48,0x3d7f3bc9,0x3d353d35,0x3d463d22,0x3d553d0e,0x3d623cf1,0x3cc43d6d,0x3cf13d62,0x3d0e3d55,0x3d223d46,0x80003d80,0x3bc93d7f,0x3c483d7b,0x3c953d75,
0xbcc43d6d,0xbc953d75,0xbc483d7b,0xbbc93d7f,0xbd353d35,0xbd223d46,0xbd0e3d55,0xbcf13d62,0xbd6d3cc4,0xbd623cf1,0xbd553d0e,0xbd463d22,0xbd800000,0xbd7f3bc9,0xbd7b3c48,0xbd753c95,
0x3d80,0xbc163d7d,0xbc953d75,0xbcdb3d67,0xbd0e3d55,0xbd2c3d3e,0xbd463d22,0xbd5c3d04,0xbd6d3cc4,0xbd783c79,0xbd7f3bc9,0xbd80bb49,0xbd7bbc48,0xbd71bcac,0xbd62bcf1,0xbd4ebd18,
0xbd35bd35,0xbd18bd4e,0xbcf1bd62,0xbcacbd71,0xbc48bd7b,0xbb49bd80,0x3bc9bd7f,0x3c79bd78,0x3cc4bd6d,0x3d04bd5c,0x3d22bd46,0x3d3ebd2c,0x3d55bd0e,0x3d67bcdb,0x3d75bc95,0x3d7dbc16,
0xbd7b3c48,0xbd7dbc16,0xbd62bcf1,0xbd2cbd3e,0x3d80,0xbcac3d71,0xbd223d46,0xbd5c3d04,0x3d55bd0e,0x3d78bc79,0x3d7f3bc9,0x3d673cdb,0xbcc4bd6d,0xbb49bd80,0x3c95bd75,0x3d18bd4e,
0xbd0e3d55,0xbd4e3d18,0xbd753c95,0xbd80bb49,0x3d353d35,0x3cdb3d67,0x3bc93d7f,0xbc793d78,0x3c48bd7b,0x3d04bd5c,0x3d46bd22,0x3d71bcac,0xbd6dbcc4,0xbd3ebd2c,0xbcf1bd62,0xbc16bd7d,
0x3d6dbcc4,0x3d7d3c16,0x3d463d22,0x3cac3d71,0xbc483d7b,0xbd2c3d3e,0xbd753c95,0xbd78bc79,0x3d80,0xbd043d5c,0xbd623cf1,0xbd80bb49,0xbd55bd0e,0xbcdbbd67,0x3bc9bd7f,0x3d18bd4e,
0xbcc43d6d,0xbd4e3d18,0xbd7f3bc9,0xbd67bcdb,0xbd0ebd55,0xbb49bd80,0x3cf1bd62,0x3d5cbd04,0xbd35bd35,0xbc79bd78,0x3c95bd75,0x3d3ebd2c,0x3d7bbc48,0x3d713cac,0x3d223d46,0x3c163d7d,
0xbd0ebd55,0x3c16bd7d,0x3d46bd22,0x3d803b49,0x3cc43d6d,0xbcac3d71,0xbd623cf1,0xbd78bc79,0xbc48bd7b,0x3d04bd5c,0x3d75bc95,0x3d673cdb,0x3d80,0xbd2c3d3e,0xbd7f3bc9,0xbd4ebd18,
0xbd7bbc48,0xbd18bd4e,0x3bc9bd7f,0x3d3ebd2c,0x3d6d3cc4,0x3cdb3d67,0xbc953d75,0xbd5c3d04,0xbd55bd0e,0xbc79bd78,0x3cf1bd62,0x3d71bcac,0x3d353d35,0x3b493d80,0xbd223d46,0xbd7d3c16,
0xbd35bd35,0x3c16bd7d,0x3d62bcf1,0x3d673cdb,0x3c483d7b,0xbd2c3d3e,0xbd7fbbc9,0xbd04bd5c,0x3cc4bd6d,0x3d78bc79,0x3d463d22,0xbb493d80,0xbd553d0e,0xbd71bcac,0xbc95bd75,0x3d18bd4e,
0x3d80,0xbd4e3d18,0xbd75bc95,0xbcacbd71,0x3d0ebd55,0x3d80bb49,0x3d223d46,0xbc793d78,0xbd6d3cc4,0xbd5cbd04,0xbbc9bd7f,0x3d3ebd2c,0x3d7b3c48,0x3cdb3d67,0xbcf13d62,0xbd7d3c16,
0x3d0ebd55,0x3d7d3c16,0x3c953d75,0xbd3e3d2c,0x3d353d35,0xbcac3d71,0xbd7f3bc9,0xbd04bd5c,0xbc483d7b,0xbd783c79,0xbd22bd46,0x3cdbbd67,0xbd6dbcc4,0xbb49bd80,0x3d62bcf1,0x3d4e3d18,
0x3d7bbc48,0x3d183d4e,0xbcf13d62,0xbd80bb49,0x3d80,0xbd673cdb,0xbd46bd22,0x3c79bd78,0xbd553d0e,0xbd5cbd04,0x3bc9bd7f,0x3d71bcac,0xbcc4bd6d,0x3d2cbd3e,0x3d753c95,0x3c163d7d,
0xbcc43d6d,0xbd7dbc16,0xbbc9bd7f,0x3d71bcac,0x3d0e3d55,0xbd2c3d3e,0xbd62bcf1,0x3c79bd78,0xbd35bd35,0x3d04bd5c,0x3d753c95,0xbb493d80,0xbd7b3c48,0xbcdbbd67,0x3d46bd22,0x3d4e3d18,
0x3d6dbcc4,0x3d183d4e,0xbd223d46,0xbd67bcdb,0x3c48bd7b,0x3d80bb49,0x3c953d75,0xbd5c3d04,0x3d80,0xbd783c79,0xbcf1bd62,0x3d3ebd2c,0x3d553d0e,0xbcac3d71,0xbd7fbbc9,0xbc16bd7d,
0x3d7b3c48,0xbc163d7d,0xbd7fbbc9,0x3b49bd80,0x3d6d3cc4,0xbcac3d71,0xbd75bc95,0x3c79bd78,0x3d553d0e,0xbd043d5c,0xbd62bcf1,0x3cdbbd67,0x3d353d35,0xbd2c3d3e,0xbd46bd22,0x3d18bd4e,
0x3d0e3d55,0xbd4e3d18,0xbd22bd46,0x3d3ebd2c,0x3cc43d6d,0xbd673cdb,0xbcf1bd62,0x3d5cbd04,0x3c483d7b,0xbd783c79,0xbc95bd75,0x3d71bcac,0x3d80,0xbd803b49,0xbbc9bd7f,0x3d7dbc16,
0xbd800000,0xbd7dbc16,0xbd75bc95,0xbd67bcdb,0xbd55bd0e,0xbd3ebd2c,0xbd22bd46,0xbd04bd5c,0xbcc4bd6d,0xbc79bd78,0xbbc9bd7f,0x3b49bd80,0x3c48bd7b,0x3cacbd71,0x3cf1bd62,0x3d18bd4e,
0x3d35bd35,0x3d4ebd18,0x3d62bcf1,0x3d71bcac,0x3d7bbc48,0x3d80bb49,0x3d7f3bc9,0x3d783c79,0x3d6d3cc4,0x3d5c3d04,0x3d463d22,0x3d2c3d3e,0x3d0e3d55,0x3cdb3d67,0x3c953d75,0x3c163d7d,
0xbc48bd7b,0x3c16bd7d,0x3cf1bd62,0x3d3ebd2c,0xbd800000,0xbd71bcac,0xbd46bd22,0xbd04bd5c,0x3d0e3d55,0x3c793d78,0xbbc93d7f,0xbcdb3d67,0x3d6dbcc4,0x3d80bb49,0x3d753c95,0x3d4e3d18,
0xbd55bd0e,0xbd18bd4e,0xbc95bd75,0x3b49bd80,0xbd353d35,0xbd673cdb,0xbd7f3bc9,0xbd78bc79,0x3d7b3c48,0x3d5c3d04,0x3d223d46,0x3cac3d71,0x3cc4bd6d,0x3d2cbd3e,0x3d62bcf1,0x3d7dbc16,
0x3cc43d6d,0xbc163d7d,0xbd223d46,0xbd713cac,0xbd7bbc48,0xbd3ebd2c,0xbc95bd75,0x3c79bd78,0xbd800000,0xbd5cbd04,0xbcf1bd62,0x3b49bd80,0x3d0ebd55,0x3d67bcdb,0x3d7f3bc9,0x3d4e3d18,
0xbd6dbcc4,0xbd18bd4e,0xbbc9bd7f,0x3cdbbd67,0x3d55bd0e,0x3d80bb49,0x3d623cf1,0x3d043d5c,0x3d35bd35,0x3d78bc79,0x3d753c95,0x3d2c3d3e,0x3c483d7b,0xbcac3d71,0xbd463d22,0xbd7d3c16,
0x3d55bd0e,0x3d7d3c16,0x3d223d46,0xbb493d80,0xbd6d3cc4,0xbd71bcac,0xbcf1bd62,0x3c79bd78,0x3d7bbc48,0x3d5c3d04,0x3c953d75,0xbcdb3d67,0xbd800000,0xbd3ebd2c,0xbbc9bd7f,0x3d18bd4e,
0x3c48bd7b,0x3d4ebd18,0x3d7f3bc9,0x3d2c3d3e,0xbcc43d6d,0xbd673cdb,0xbd75bc95,0xbd04bd5c,0x3d0ebd55,0x3d78bc79,0x3d623cf1,0x3cac3d71,0xbd353d35,0xbd803b49,0xbd46bd22,0xbc16bd7d,
0x3d35bd35,0x3d7d3c16,0x3cf13d62,0xbcdb3d67,0xbd7b3c48,0xbd3ebd2c,0x3bc9bd7f,0x3d5cbd04,0x3d6d3cc4,0x3c793d78,0xbd223d46,0xbd80bb49,0xbd0ebd55,0x3cacbd71,0x3d75bc95,0x3d4e3d18,
0xbd800000,0xbd18bd4e,0x3c95bd75,0x3d71bcac,0x3d553d0e,0x3b493d80,0xbd463d22,0xbd78bc79,0xbcc4bd6d,0x3d04bd5c,0x3d7fbbc9,0x3d2c3d3e,0xbc483d7b,0xbd673cdb,0xbd62bcf1,0xbc16bd7d,
0x3d553d0e,0xbc163d7d,0xbd753c95,0xbd2cbd3e,0xbd353d35,0xbd71bcac,0xbbc9bd7f,0x3d5cbd04,0xbd7bbc48,0xbc79bd78,0x3d46bd22,0x3d673cdb,0x3cc4bd6d,0x3d80bb49,0x3cf13d62,0xbd183d4e,
0x3c483d7b,0xbd4e3d18,0xbd62bcf1,0x3b49bd80,0xbd800000,0xbcdbbd67,0x3d22bd46,0x3d783c79,0xbd0ebd55,0x3d04bd5c,0x3d7f3bc9,0x3cac3d71,0x3d6dbcc4,0x3d3e3d2c,0xbc953d75,0xbd7d3c16,
0xbd6dbcc4,0x3c16bd7d,0x3d7fbbc9,0x3cac3d71,0xbd553d0e,0xbd3ebd2c,0x3cf1bd62,0x3d783c79,0x3d35bd35,0x3d5c3d04,0xbc953d75,0xbd80bb49,0xbc48bd7b,0x3d67bcdb,0x3d223d46,0xbd183d4e,
0x3cc43d6d,0xbd4e3d18,0xbd46bd22,0x3cdbbd67,0x3d7b3c48,0x3b493d80,0xbd753c95,0xbd04bd5c,0xbd800000,0xbc79bd78,0x3d62bcf1,0x3d2c3d3e,0xbd0e3d55,0xbd71bcac,0x3bc9bd7f,0x3d7dbc16,
0xbc483d7b,0xbd7dbc16,0x3bc9bd7f,0x3d803b49,0xbcc43d6d,0xbd71bcac,0x3c95bd75,0x3d783c79,0xbd0e3d55,0xbd5cbd04,0x3cf1bd62,0x3d673cdb,0xbd353d35,0xbd3ebd2c,0x3d22bd46,0x3d4e3d18,
0xbd553d0e,0xbd18bd4e,0x3d46bd22,0x3d2c3d3e,0xbd6d3cc4,0xbcdbbd67,0x3d62bcf1,0x3d043d5c,0xbd7b3c48,0xbc79bd78,0x3d75bc95,0x3cac3d71,0xbd800000,0xbb49bd80,0x3d7fbbc9,0x3c163d7d,
0x3d80,0xbd7dbc16,0x3c95bd75,0x3d673cdb,0xbd0e3d55,0xbd3ebd2c,0x3d46bd22,0x3d043d5c,0xbd6d3cc4,0xbc79bd78,0x3d7fbbc9,0xbb493d80,0xbd7bbc48,0x3cacbd71,0x3d623cf1,0xbd183d4e,
0xbd35bd35,0x3d4ebd18,0x3cf13d62,0xbd713cac,0xbc48bd7b,0x3d80bb49,0xbbc93d7f,0xbd78bc79,0x3cc4bd6d,0x3d5c3d04,0xbd223d46,0xbd2cbd3e,0x3d55bd0e,0x3cdb3d67,0xbd753c95,0xbc16bd7d,
0xbd7b3c48,0x3c16bd7d,0x3d623cf1,0xbd3e3d2c,0x3d80,0xbd71bcac,0x3d22bd46,0x3d043d5c,0x3d55bd0e,0x3c793d78,0xbd7fbbc9,0x3cdbbd67,0xbcc4bd6d,0x3d80bb49,0xbc953d75,0xbd4ebd18,
0xbd0e3d55,0xbd18bd4e,0x3d75bc95,0xbb493d80,0x3d353d35,0xbd673cdb,0xbbc9bd7f,0x3d783c79,0x3c48bd7b,0x3d5c3d04,0xbd463d22,0xbcacbd71,0xbd6dbcc4,0x3d2cbd3e,0x3cf13d62,0xbd7d3c16,
0x3d6dbcc4,0xbc163d7d,0xbd46bd22,0x3d71bcac,0xbc483d7b,0xbd3ebd2c,0x3d75bc95,0xbc793d78,0x3d80,0xbd5cbd04,0x3d62bcf1,0xbb493d80,0xbd55bd0e,0x3d67bcdb,0xbbc93d7f,0xbd4ebd18,
0xbcc43d6d,0xbd18bd4e,0x3d7fbbc9,0xbcdb3d67,0xbd0ebd55,0x3d80bb49,0xbcf13d62,0xbd04bd5c,0xbd35bd35,0x3d78bc79,0xbc953d75,0xbd2cbd3e,0x3d7bbc48,0xbcac3d71,0xbd22bd46,0x3d7dbc16,
0xbd0ebd55,0x3d7d3c16,0xbd463d22,0x3b49bd80,0x3cc43d6d,0xbd71bcac,0x3d62bcf1,0xbc793d78,0xbc48bd7b,0x3d5c3d04,0xbd753c95,0x3cdbbd67,0x3d80,0xbd3ebd2c,0x3d7fbbc9,0xbd183d4e,
0xbd7bbc48,0x3d4ebd18,0xbbc93d7f,0xbd2cbd3e,0x3d6d3cc4,0xbd673cdb,0x3c95bd75,0x3d043d5c,0xbd55bd0e,0x3d78bc79,0xbcf13d62,0xbcacbd71,0x3d353d35,0xbd803b49,0x3d22bd46,0x3c163d7d,
0xbd35bd35,0x3d7d3c16,0xbd623cf1,0x3cdbbd67,0x3c483d7b,0xbd3ebd2c,0x3d7f3bc9,0xbd5c3d04,0x3cc4bd6d,0x3c793d78,0xbd46bd22,0x3d803b49,0xbd553d0e,0x3cacbd71,0x3c953d75,0xbd4ebd18,
0x3d80,0xbd18bd4e,0x3d753c95,0xbd713cac,0x3d0ebd55,0x3b493d80,0xbd22bd46,0x3d783c79,0xbd6d3cc4,0x3d04bd5c,0x3bc93d7f,0xbd2cbd3e,0x3d7b3c48,0xbd673cdb,0x3cf1bd62,0x3c163d7d,
0x3d0ebd55,0xbc163d7d,0xbc95bd75,0x3d2c3d3e,0x3d353d35,0xbd71bcac,0x3d7fbbc9,0xbd5c3d04,0xbc483d7b,0xbc79bd78,0x3d223d46,0xbd67bcdb,0xbd6dbcc4,0x3d80bb49,0xbd623cf1,0x3d18bd4e,
0x3d7bbc48,0xbd4e3d18,0x3cf1bd62,0xbb493d80,0x3d80,0xbcdbbd67,0x3d463d22,0xbd78bc79,0xbd553d0e,0x3d04bd5c,0xbbc93d7f,0xbcacbd71,0xbcc4bd6d,0x3d3e3d2c,0xbd75bc95,0x3d7dbc16,
0xbcc43d6d,0x3c16bd7d,0x3bc93d7f,0xbcacbd71,0x3d0e3d55,0xbd3ebd2c,0x3d623cf1,0xbd78bc79,0xbd35bd35,0x3d5c3d04,0xbd75bc95,0x3d803b49,0xbd7b3c48,0x3d67bcdb,0xbd463d22,0x3d18bd4e,
0x3d6dbcc4,0xbd4e3d18,0x3d22bd46,0xbcdb3d67,0x3c48bd7b,0x3b493d80,0xbc95bd75,0x3d043d5c,0x3d80,0xbc79bd78,0x3cf13d62,0xbd2cbd3e,0x3d553d0e,0xbd71bcac,0x3d7f3bc9,0xbd7d3c16,
0x3d7b3c48,0xbd7dbc16,0x3d7f3bc9,0xbd80bb49,0x3d6d3cc4,0xbd71bcac,0x3d753c95,0xbd78bc79,0x3d553d0e,0xbd5cbd04,0x3d623cf1,0xbd67bcdb,0x3d353d35,0xbd3ebd2c,0x3d463d22,0xbd4ebd18,
0x3d0e3d55,0xbd18bd4e,0x3d223d46,0xbd2cbd3e,0x3cc43d6d,0xbcdbbd67,0x3cf13d62,0xbd04bd5c,0x3c483d7b,0xbc79bd78,0x3c953d75,0xbcacbd71,0x3d80,0xbb49bd80,0x3bc93d7f,0xbc16bd7d,
0xbd800000,0x3c16bd7d,0x3d753c95,0xbcdb3d67,0xbd55bd0e,0x3d2cbd3e,0x3d223d46,0xbd5c3d04,0xbcc4bd6d,0x3d78bc79,0x3bc93d7f,0xbd80bb49,0x3c48bd7b,0x3d713cac,0xbcf13d62,0xbd4ebd18,
0x3d35bd35,0x3d183d4e,0xbd623cf1,0xbcacbd71,0x3d7bbc48,0x3b493d80,0xbd7fbbc9,0x3c79bd78,0x3d6d3cc4,0xbd043d5c,0xbd46bd22,0x3d3ebd2c,0x3d0e3d55,0xbd673cdb,0xbc95bd75,0x3d7dbc16,
0xbc48bd7b,0x3d7d3c16,0xbcf13d62,0xbd2cbd3e,0xbd800000,0x3cacbd71,0x3d463d22,0xbd5c3d04,0x3d0e3d55,0xbd783c79,0x3bc9bd7f,0x3d673cdb,0x3d6dbcc4,0x3b493d80,0xbd75bc95,0x3d18bd4e,
0xbd55bd0e,0x3d4ebd18,0x3c953d75,0xbd80bb49,0xbd353d35,0xbcdbbd67,0x3d7fbbc9,0xbc793d78,0x3d7b3c48,0xbd043d5c,0xbd22bd46,0x3d71bcac,0x3cc4bd6d,0x3d3e3d2c,0xbd623cf1,0xbc16bd7d,
0x3cc43d6d,0xbd7dbc16,0x3d22bd46,0x3cac3d71,0xbd7bbc48,0x3d2cbd3e,0x3c953d75,0xbd78bc79,0xbd800000,0x3d04bd5c,0x3cf13d62,0xbd80bb49,0x3d0ebd55,0x3cdb3d67,0xbd7fbbc9,0x3d18bd4e,
0xbd6dbcc4,0x3d4ebd18,0x3bc93d7f,0xbd67bcdb,0x3d55bd0e,0x3b493d80,0xbd62bcf1,0x3d5cbd04,0x3d35bd35,0x3c793d78,0xbd75bc95,0x3d3ebd2c,0x3c483d7b,0xbd71bcac,0x3d46bd22,0x3c163d7d,
0x3d55bd0e,0xbc163d7d,0xbd22bd46,0x3d803b49,0xbd6d3cc4,0x3cacbd71,0x3cf13d62,0xbd78bc79,0x3d7bbc48,0xbd043d5c,0xbc95bd75,0x3d673cdb,0xbd800000,0x3d2cbd3e,0x3bc93d7f,0xbd4ebd18,
0x3c48bd7b,0x3d183d4e,0xbd7fbbc9,0x3d3ebd2c,0xbcc43d6d,0xbcdbbd67,0x3d753c95,0xbd5c3d04,0x3d0ebd55,0x3c793d78,0xbd62bcf1,0x3d71bcac,0xbd353d35,0xbb49bd80,0x3d463d22,0xbd7d3c16,
0x3d35bd35,0xbc163d7d,0xbcf1bd62,0x3d673cdb,0xbd7b3c48,0x3d2cbd3e,0xbbc93d7f,0xbd04bd5c,0x3d6d3cc4,0xbd783c79,0x3d22bd46,0xbb493d80,0xbd0ebd55,0x3d713cac,0xbd753c95,0x3d18bd4e,
0xbd800000,0x3d4ebd18,0xbc953d75,0xbcacbd71,0x3d553d0e,0xbd803b49,0x3d46bd22,0xbc793d78,0xbcc4bd6d,0x3d5c3d04,0xbd7f3bc9,0x3d3ebd2c,0xbc483d7b,0xbcdbbd67,0x3d623cf1,0xbd7d3c16,
0x3d553d0e,0xbd7dbc16,0x3d75bc95,0xbd3e3d2c,0xbd353d35,0x3cacbd71,0x3bc93d7f,0xbd04bd5c,0xbd7bbc48,0x3d78bc79,0xbd463d22,0x3cdbbd67,0x3cc4bd6d,0x3b493d80,0xbcf1bd62,0x3d4e3d18,
0x3c483d7b,0xbd18bd4e,0x3d623cf1,0xbd80bb49,0xbd800000,0x3d67bcdb,0xbd223d46,0x3c79bd78,0xbd0ebd55,0x3d5c3d04,0xbd7fbbc9,0x3d71bcac,0x3d6dbcc4,0xbd2c3d3e,0x3c95bd75,0x3c163d7d,
0xbd6dbcc4,0x3d7d3c16,0xbd7f3bc9,0x3d71bcac,0xbd553d0e,0x3d2cbd3e,0xbcf13d62,0x3c79bd78,0x3d35bd35,0xbd043d5c,0x3c95bd75,0xbb493d80,0xbc48bd7b,0x3cdb3d67,0xbd22bd46,0x3d4e3d18,
0x3cc43d6d,0xbd18bd4e,0x3d463d22,0xbd67bcdb,0x3d7b3c48,0xbd803b49,0x3d75bc95,0xbd5c3d04,0xbd800000,0x3d78bc79,0xbd623cf1,0x3d3ebd2c,0xbd0e3d55,0x3cacbd71,0xbbc93d7f,0xbc16bd7d,
0xbc483d7b,0x3c16bd7d,0xbbc93d7f,0x3b49bd80,0xbcc43d6d,0x3cacbd71,0xbc953d75,0x3c79bd78,0xbd0e3d55,0x3d04bd5c,0xbcf13d62,0x3cdbbd67,0xbd353d35,0x3d2cbd3e,0xbd223d46,0x3d18bd4e,
0xbd553d0e,0x3d4ebd18,0xbd463d22,0x3d3ebd2c,0xbd6d3cc4,0x3d67bcdb,0xbd623cf1,0x3d5cbd04,0xbd7b3c48,0x3d78bc79,0xbd753c95,0x3d71bcac,0xbd800000,0x3d80bb49,0xbd7f3bc9,0x3d7dbc16,
0x3d80,0x3c16bd7d,0xbc953d75,0x3cdbbd67,0xbd0e3d55,0x3d2cbd3e,0xbd463d22,0x3d5cbd04,0xbd6d3cc4,0x3d78bc79,0xbd7f3bc9,0x3d803b49,0xbd7bbc48,0x3d713cac,0xbd62bcf1,0x3d4e3d18,
0xbd35bd35,0x3d183d4e,0xbcf1bd62,0x3cac3d71,0xbc48bd7b,0x3b493d80,0x3bc9bd7f,0xbc793d78,0x3cc4bd6d,0xbd043d5c,0x3d22bd46,0xbd3e3d2c,0x3d55bd0e,0xbd673cdb,0x3d75bc95,0xbd7d3c16,
0xbd7b3c48,0x3d7d3c16,0xbd62bcf1,0x3d2c3d3e,0x3d80,0x3cacbd71,0xbd223d46,0x3d5cbd04,0x3d55bd0e,0xbd783c79,0x3d7f3bc9,0xbd67bcdb,0xbcc4bd6d,0x3b493d80,0x3c95bd75,0xbd183d4e,
0xbd0e3d55,0x3d4ebd18,0xbd753c95,0x3d803b49,0x3d353d35,0xbcdbbd67,0x3bc93d7f,0x3c79bd78,0x3c48bd7b,0xbd043d5c,0x3d46bd22,0xbd713cac,0xbd6dbcc4,0x3d3e3d2c,0xbcf1bd62,0x3c163d7d,
0x3d6dbcc4,0xbd7dbc16,0x3d463d22,0xbcacbd71,0xbc483d7b,0x3d2cbd3e,0xbd753c95,0x3d783c79,0x3d80,0x3d04bd5c,0xbd623cf1,0x3d803b49,0xbd55bd0e,0x3cdb3d67,0x3bc9bd7f,0xbd183d4e,
0xbcc43d6d,0x3d4ebd18,0xbd7f3bc9,0x3d673cdb,0xbd0ebd55,0x3b493d80,0x3cf1bd62,0xbd5c3d04,0xbd35bd35,0x3c793d78,0x3c95bd75,0xbd3e3d2c,0x3d7bbc48,0xbd71bcac,0x3d223d46,0xbc16bd7d,
0xbd0ebd55,0xbc163d7d,0x3d46bd22,0xbd80bb49,0x3cc43d6d,0x3cacbd71,0xbd623cf1,0x3d783c79,0xbc48bd7b,0xbd043d5c,0x3d75bc95,0xbd67bcdb,0x3d80,0x3d2cbd3e,0xbd7f3bc9,0x3d4e3d18,
0xbd7bbc48,0x3d183d4e,0x3bc9bd7f,0xbd3e3d2c,0x3d6d3cc4,0xbcdbbd67,0xbc953d75,0x3d5cbd04,0xbd55bd0e,0x3c793d78,0x3cf1bd62,0xbd713cac,0x3d353d35,0xbb49bd80,0xbd223d46,0x3d7dbc16,
0xbd35bd35,0xbc163d7d,0x3d62bcf1,0xbd67bcdb,0x3c483d7b,0x3d2cbd3e,0xbd7fbbc9,0x3d043d5c,0x3cc4bd6d,0xbd783c79,0x3d463d22,0x3b49bd80,0xbd553d0e,0x3d713cac,0xbc95bd75,0xbd183d4e,
0x3d80,0x3d4ebd18,0xbd75bc95,0x3cac3d71,0x3d0ebd55,0xbd803b49,0x3d223d46,0x3c79bd78,0xbd6d3cc4,0x3d5c3d04,0xbbc9bd7f,0xbd3e3d2c,0x3d7b3c48,0xbcdbbd67,0xbcf13d62,0x3d7dbc16,
0x3d0ebd55,0xbd7dbc16,0x3c953d75,0x3d3ebd2c,0x3d353d35,0x3cacbd71,0xbd7f3bc9,0x3d043d5c,0xbc483d7b,0x3d78bc79,0xbd22bd46,0xbcdb3d67,0xbd6dbcc4,0x3b493d80,0x3d62bcf1,0xbd4ebd18,
0x3d7bbc48,0xbd18bd4e,0xbcf13d62,0x3d803b49,0x3d80,0x3d67bcdb,0xbd46bd22,0xbc793d78,0xbd553d0e,0x3d5c3d04,0x3bc9bd7f,0xbd713cac,0xbcc4bd6d,0xbd2c3d3e,0x3d753c95,0xbc16bd7d,
0xbcc43d6d,0x3d7d3c16,0xbbc9bd7f,0xbd713cac,0x3d0e3d55,0x3d2cbd3e,0xbd62bcf1,0xbc793d78,0xbd35bd35,0xbd043d5c,0x3d753c95,0x3b49bd80,0xbd7b3c48,0x3cdb3d67,0x3d46bd22,0xbd4ebd18,
0x3d6dbcc4,0xbd18bd4e,0xbd223d46,0x3d673cdb,0x3c48bd7b,0xbd803b49,0x3c953d75,0x3d5cbd04,0x3d80,0x3d78bc79,0xbcf1bd62,0xbd3e3d2c,0x3d553d0e,0x3cacbd71,0xbd7fbbc9,0x3c163d7d,
0x3d7b3c48,0x3c16bd7d,0xbd7fbbc9,0xbb493d80,0x3d6d3cc4,0x3cacbd71,0xbd75bc95,0xbc793d78,0x3d553d0e,0x3d04bd5c,0xbd62bcf1,0xbcdb3d67,0x3d353d35,0x3d2cbd3e,0xbd46bd22,0xbd183d4e,
0x3d0e3d55,0x3d4ebd18,0xbd22bd46,0xbd3e3d2c,0x3cc43d6d,0x3d67bcdb,0xbcf1bd62,0xbd5c3d04,0x3c483d7b,0x3d78bc79,0xbc95bd75,0xbd713cac,0x3d80,0x3d80bb49,0xbbc9bd7f,0xbd7d3c16,
0xbd800000,0x3d7d3c16,0xbd75bc95,0x3d673cdb,0xbd55bd0e,0x3d3e3d2c,0xbd22bd46,0x3d043d5c,0xbcc4bd6d,0x3c793d78,0xbbc9bd7f,0xbb493d80,0x3c48bd7b,0xbcac3d71,0x3cf1bd62,0xbd183d4e,
0x3d35bd35,0xbd4e3d18,0x3d62bcf1,0xbd713cac,0x3d7bbc48,0xbd803b49,0x3d7f3bc9,0xbd78bc79,0x3d6d3cc4,0xbd5cbd04,0x3d463d22,0xbd2cbd3e,0x3d0e3d55,0xbcdbbd67,0x3c953d75,0xbc16bd7d,
0xbc48bd7b,0xbc163d7d,0x3cf1bd62,0xbd3e3d2c,0xbd800000,0x3d713cac,0xbd46bd22,0x3d043d5c,0x3d0e3d55,0xbc79bd78,0xbbc93d7f,0x3cdbbd67,0x3d6dbcc4,0xbd803b49,0x3d753c95,0xbd4ebd18,
0xbd55bd0e,0x3d183d4e,0xbc95bd75,0xbb493d80,0xbd353d35,0x3d67bcdb,0xbd7f3bc9,0x3d783c79,0x3d7b3c48,0xbd5cbd04,0x3d223d46,0xbcacbd71,0x3cc4bd6d,0xbd2c3d3e,0x3d62bcf1,0xbd7d3c16,
0x3cc43d6d,0x3c16bd7d,0xbd223d46,0x3d71bcac,0xbd7bbc48,0x3d3e3d2c,0xbc95bd75,0xbc793d78,0xbd800000,0x3d5c3d04,0xbcf1bd62,0xbb493d80,0x3d0ebd55,0xbd673cdb,0x3d7f3bc9,0xbd4ebd18,
0xbd6dbcc4,0x3d183d4e,0xbbc9bd7f,0xbcdb3d67,0x3d55bd0e,0xbd803b49,0x3d623cf1,0xbd04bd5c,0x3d35bd35,0xbd783c79,0x3d753c95,0xbd2cbd3e,0x3c483d7b,0x3cacbd71,0xbd463d22,0x3d7dbc16,
0x3d55bd0e,0xbd7dbc16,0x3d223d46,0x3b49bd80,0xbd6d3cc4,0x3d713cac,0xbcf1bd62,0xbc793d78,0x3d7bbc48,0xbd5cbd04,0x3c953d75,0x3cdbbd67,0xbd800000,0x3d3e3d2c,0xbbc9bd7f,0xbd183d4e,
0x3c48bd7b,0xbd4e3d18,0x3d7f3bc9,0xbd2cbd3e,0xbcc43d6d,0x3d67bcdb,0xbd75bc95,0x3d043d5c,0x3d0ebd55,0xbd783c79,0x3d623cf1,0xbcacbd71,0xbd353d35,0x3d80bb49,0xbd46bd22,0x3c163d7d,
0x3d35bd35,0xbd7dbc16,0x3cf13d62,0x3cdbbd67,0xbd7b3c48,0x3d3e3d2c,0x3bc9bd7f,0xbd5c3d04,0x3d6d3cc4,0xbc79bd78,0xbd223d46,0x3d803b49,0xbd0ebd55,0xbcac3d71,0x3d75bc95,0xbd4ebd18,
0xbd800000,0x3d183d4e,0x3c95bd75,0xbd713cac,0x3d553d0e,0xbb49bd80,0xbd463d22,0x3d783c79,0xbcc4bd6d,0xbd043d5c,0x3d7fbbc9,0xbd2cbd3e,0xbc483d7b,0x3d67bcdb,0xbd62bcf1,0x3c163d7d,
0x3d553d0e,0x3c16bd7d,0xbd753c95,0x3d2c3d3e,0xbd353d35,0x3d713cac,0xbbc9bd7f,0xbd5c3d04,0xbd7bbc48,0x3c793d78,0x3d46bd22,0xbd67bcdb,0x3cc4bd6d,0xbd803b49,0x3cf13d62,0x3d18bd4e,
0x3c483d7b,0x3d4ebd18,0xbd62bcf1,0xbb493d80,0xbd800000,0x3cdb3d67,0x3d22bd46,0xbd78bc79,0xbd0ebd55,0xbd043d5c,0x3d7f3bc9,0xbcacbd71,0x3d6dbcc4,0xbd3ebd2c,0xbc953d75,0x3d7dbc16,
0xbd6dbcc4,0xbc163d7d,0x3d7fbbc9,0xbcacbd71,0xbd553d0e,0x3d3e3d2c,0x3cf1bd62,0xbd78bc79,0x3d35bd35,0xbd5cbd04,0xbc953d75,0x3d803b49,0xbc48bd7b,0xbd673cdb,0x3d223d46,0x3d18bd4e,
0x3cc43d6d,0x3d4ebd18,0xbd46bd22,0xbcdb3d67,0x3d7b3c48,0xbb49bd80,0xbd753c95,0x3d043d5c,0xbd800000,0x3c793d78,0x3d62bcf1,0xbd2cbd3e,0xbd0e3d55,0x3d713cac,0x3bc9bd7f,0xbd7d3c16,
0xbc483d7b,0x3d7d3c16,0x3bc9bd7f,0xbd80bb49,0xbcc43d6d,0x3d713cac,0x3c95bd75,0xbd78bc79,0xbd0e3d55,0x3d5c3d04,0x3cf1bd62,0xbd67bcdb,0xbd353d35,0x3d3e3d2c,0x3d22bd46,0xbd4ebd18,
0xbd553d0e,0x3d183d4e,0x3d46bd22,0xbd2cbd3e,0xbd6d3cc4,0x3cdb3d67,0x3d62bcf1,0xbd04bd5c,0xbd7b3c48,0x3c793d78,0x3d75bc95,0xbcacbd71,0xbd800000,0x3b493d80,0x3d7fbbc9,0xbc16bd7d,
0x3d80,0x3d7d3c16,0x3c95bd75,0xbd67bcdb,0xbd0e3d55,0x3d3e3d2c,0x3d46bd22,0xbd04bd5c,0xbd6d3cc4,0x3c793d78,0x3d7fbbc9,0x3b49bd80,0xbd7bbc48,0xbcac3d71,0x3d623cf1,0x3d18bd4e,
0xbd35bd35,0xbd4e3d18,0x3cf13d62,0x3d71bcac,0xbc48bd7b,0xbd803b49,0xbbc93d7f,0x3d783c79,0x3cc4bd6d,0xbd5cbd04,0xbd223d46,0x3d2c3d3e,0x3d55bd0e,0xbcdbbd67,0xbd753c95,0x3c163d7d,
0xbd7b3c48,0xbc163d7d,0x3d623cf1,0x3d3ebd2c,0x3d80,0x3d713cac,0x3d22bd46,0xbd04bd5c,0x3d55bd0e,0xbc79bd78,0xbd7fbbc9,0xbcdb3d67,0xbcc4bd6d,0xbd803b49,0xbc953d75,0x3d4e3d18,
0xbd0e3d55,0x3d183d4e,0x3d75bc95,0x3b49bd80,0x3d353d35,0x3d67bcdb,0xbbc9bd7f,0xbd78bc79,0x3c48bd7b,0xbd5cbd04,0xbd463d22,0x3cac3d71,0xbd6dbcc4,0xbd2c3d3e,0x3cf13d62,0x3d7dbc16,
0x3d6dbcc4,0x3c16bd7d,0xbd46bd22,0xbd713cac,0xbc483d7b,0x3d3e3d2c,0x3d75bc95,0x3c79bd78,0x3d80,0x3d5c3d04,0x3d62bcf1,0x3b49bd80,0xbd55bd0e,0xbd673cdb,0xbbc93d7f,0x3d4e3d18,
0xbcc43d6d,0x3d183d4e,0x3d7fbbc9,0x3cdbbd67,0xbd0ebd55,0xbd803b49,0xbcf13d62,0x3d043d5c,0xbd35bd35,0xbd783c79,0xbc953d75,0x3d2c3d3e,0x3d7bbc48,0x3cacbd71,0xbd22bd46,0xbd7d3c16,
0xbd0ebd55,0xbd7dbc16,0xbd463d22,0xbb493d80,0x3cc43d6d,0x3d713cac,0x3d62bcf1,0x3c79bd78,0xbc48bd7b,0xbd5cbd04,0xbd753c95,0xbcdb3d67,0x3d80,0x3d3e3d2c,0x3d7fbbc9,0x3d18bd4e,
0xbd7bbc48,0xbd4e3d18,0xbbc93d7f,0x3d2c3d3e,0x3d6d3cc4,0x3d67bcdb,0x3c95bd75,0xbd04bd5c,0xbd55bd0e,0xbd783c79,0xbcf13d62,0x3cac3d71,0x3d353d35,0x3d80bb49,0x3d22bd46,0xbc16bd7d,
0xbd35bd35,0xbd7dbc16,0xbd623cf1,0xbcdb3d67,0x3c483d7b,0x3d3e3d2c,0x3d7f3bc9,0x3d5cbd04,0x3cc4bd6d,0xbc79bd78,0xbd46bd22,0xbd80bb49,0xbd553d0e,0xbcac3d71,0x3c953d75,0x3d4e3d18,
0x3d80,0x3d183d4e,0x3d753c95,0x3d71bcac,0x3d0ebd55,0xbb49bd80,0xbd22bd46,0xbd78bc79,0xbd6d3cc4,0xbd043d5c,0x3bc93d7f,0x3d2c3d3e,0x3d7b3c48,0x3d67bcdb,0x3cf1bd62,0xbc16bd7d,
0x3d0ebd55,0x3c16bd7d,0xbc95bd75,0xbd2cbd3e,0x3d353d35,0x3d713cac,0x3d7fbbc9,0x3d5cbd04,0xbc483d7b,0x3c793d78,0x3d223d46,0x3d673cdb,0xbd6dbcc4,0xbd803b49,0xbd623cf1,0xbd183d4e,
0x3d7bbc48,0x3d4ebd18,0x3cf1bd62,0x3b49bd80,0x3d80,0x3cdb3d67,0x3d463d22,0x3d783c79,0xbd553d0e,0xbd043d5c,0xbbc93d7f,0x3cac3d71,0xbcc4bd6d,0xbd3ebd2c,0xbd75bc95,0xbd7d3c16,
0xbcc43d6d,0xbc163d7d,0x3bc93d7f,0x3cac3d71,0x3d0e3d55,0x3d3e3d2c,0x3d623cf1,0x3d783c79,0xbd35bd35,0xbd5cbd04,0xbd75bc95,0xbd80bb49,0xbd7b3c48,0xbd673cdb,0xbd463d22,0xbd183d4e,
0x3d6dbcc4,0x3d4ebd18,0x3d22bd46,0x3cdbbd67,0x3c48bd7b,0xbb49bd80,0xbc95bd75,0xbd04bd5c,0x3d80,0x3c793d78,0x3cf13d62,0x3d2c3d3e,0x3d553d0e,0x3d713cac,0x3d7f3bc9,0x3d7dbc16,
0x3d7b3c48,0x3d7d3c16,0x3d7f3bc9,0x3d803b49,0x3d6d3cc4,0x3d713cac,0x3d753c95,0x3d783c79,0x3d553d0e,0x3d5c3d04,0x3d623cf1,0x3d673cdb,0x3d353d35,0x3d3e3d2c,0x3d463d22,0x3d4e3d18,
0x3d0e3d55,0x3d183d4e,0x3d223d46,0x3d2c3d3e,0x3cc43d6d,0x3cdb3d67,0x3cf13d62,0x3d043d5c,0x3c483d7b,0x3c793d78,0x3c953d75,0x3cac3d71,0x3d80,0x3b493d80,0x3bc93d7f,0x3c163d7d,
0xbd800000,0xbc163d7d,0x3d753c95,0x3cdbbd67,0xbd55bd0e,0xbd2c3d3e,0x3d223d46,0x3d5cbd04,0xbcc4bd6d,0xbd783c79,0x3bc93d7f,0x3d803b49,0x3c48bd7b,0xbd71bcac,0xbcf13d62,0x3d4e3d18,
0x3d35bd35,0xbd18bd4e,0xbd623cf1,0x3cac3d71,0x3d7bbc48,0xbb49bd80,0xbd7fbbc9,0xbc793d78,0x3d6d3cc4,0x3d04bd5c,0xbd46bd22,0xbd3e3d2c,0x3d0e3d55,0x3d67bcdb,0xbc95bd75,0xbd7d3c16,
0xbc48bd7b,0xbd7dbc16,0xbcf13d62,0x3d2c3d3e,0xbd800000,0xbcac3d71,0x3d463d22,0x3d5cbd04,0x3d0e3d55,0x3d78bc79,0x3bc9bd7f,0xbd67bcdb,0x3d6dbcc4,0xbb49bd80,0xbd75bc95,0xbd183d4e,
0xbd55bd0e,0xbd4e3d18,0x3c953d75,0x3d803b49,0xbd353d35,0x3cdb3d67,0x3d7fbbc9,0x3c79bd78,0x3d7b3c48,0x3d04bd5c,0xbd22bd46,0xbd713cac,0x3cc4bd6d,0xbd3ebd2c,0xbd623cf1,0x3c163d7d,
0x3cc43d6d,0x3d7d3c16,0x3d22bd46,0xbcacbd71,0xbd7bbc48,0xbd2c3d3e,0x3c953d75,0x3d783c79,0xbd800000,0xbd043d5c,0x3cf13d62,0x3d803b49,0x3d0ebd55,0xbcdbbd67,0xbd7fbbc9,0xbd183d4e,
0xbd6dbcc4,0xbd4e3d18,0x3bc93d7f,0x3d673cdb,0x3d55bd0e,0xbb49bd80,0xbd62bcf1,0xbd5c3d04,0x3d35bd35,0xbc79bd78,0xbd75bc95,0xbd3e3d2c,0x3c483d7b,0x3d713cac,0x3d46bd22,0xbc16bd7d,
0x3d55bd0e,0x3c16bd7d,0xbd22bd46,0xbd80bb49,0xbd6d3cc4,0xbcac3d71,0x3cf13d62,0x3d783c79,0x3d7bbc48,0x3d04bd5c,0xbc95bd75,0xbd67bcdb,0xbd800000,0xbd2c3d3e,0x3bc93d7f,0x3d4e3d18,
0x3c48bd7b,0xbd18bd4e,0xbd7fbbc9,0xbd3e3d2c,0xbcc43d6d,0x3cdb3d67,0x3d753c95,0x3d5cbd04,0x3d0ebd55,0xbc79bd78,0xbd62bcf1,0xbd713cac,0xbd353d35,0x3b493d80,0x3d463d22,0x3d7dbc16,
0x3d35bd35,0x3c16bd7d,0xbcf1bd62,0xbd67bcdb,0xbd7b3c48,0xbd2c3d3e,0xbbc93d7f,0x3d043d5c,0x3d6d3cc4,0x3d78bc79,0x3d22bd46,0x3b49bd80,0xbd0ebd55,0xbd71bcac,0xbd753c95,0xbd183d4e,
0xbd800000,0xbd4e3d18,0xbc953d75,0x3cac3d71,0x3d553d0e,0x3d80bb49,0x3d46bd22,0x3c79bd78,0xbcc4bd6d,0xbd5cbd04,0xbd7f3bc9,0xbd3e3d2c,0xbc483d7b,0x3cdb3d67,0x3d623cf1,0x3d7dbc16,
0x3d553d0e,0x3d7d3c16,0x3d75bc95,0x3d3ebd2c,0xbd353d35,0xbcac3d71,0x3bc93d7f,0x3d043d5c,0xbd7bbc48,0xbd783c79,0xbd463d22,0xbcdb3d67,0x3cc4bd6d,0xbb49bd80,0xbcf1bd62,0xbd4ebd18,
0x3c483d7b,0x3d183d4e,0x3d623cf1,0x3d803b49,0xbd800000,0xbd673cdb,0xbd223d46,0xbc793d78,0xbd0ebd55,0xbd5cbd04,0xbd7fbbc9,0xbd713cac,0x3d6dbcc4,0x3d2cbd3e,0x3c95bd75,0xbc16bd7d,
0xbd6dbcc4,0xbd7dbc16,0xbd7f3bc9,0xbd713cac,0xbd553d0e,0xbd2c3d3e,0xbcf13d62,0xbc793d78,0x3d35bd35,0x3d04bd5c,0x3c95bd75,0x3b49bd80,0xbc48bd7b,0xbcdbbd67,0xbd22bd46,0xbd4ebd18,
0x3cc43d6d,0x3d183d4e,0x3d463d22,0x3d673cdb,0x3d7b3c48,0x3d80bb49,0x3d75bc95,0x3d5cbd04,0xbd800000,0xbd783c79,0xbd623cf1,0xbd3e3d2c,0xbd0e3d55,0xbcac3d71,0xbbc93d7f,0x3c163d7d,
0xbc483d7b,0xbc163d7d,0xbbc93d7f,0xbb493d80,0xbcc43d6d,0xbcac3d71,0xbc953d75,0xbc793d78,0xbd0e3d55,0xbd043d5c,0xbcf13d62,0xbcdb3d67,0xbd353d35,0xbd2c3d3e,0xbd223d46,0xbd183d4e,
0xbd553d0e,0xbd4e3d18,0xbd463d22,0xbd3e3d2c,0xbd6d3cc4,0xbd673cdb,0xbd623cf1,0xbd5c3d04,0xbd7b3c48,0xbd783c79,0xbd753c95,0xbd713cac,0xbd800000,0xbd803b49,0xbd7f3bc9,0xbd7d3c16,
0x3f003f00,0xbf003f00,0x3f003f00,0xbf003f00,0x3f003f00,0xbf003f00,0x3f003f00,0xbf003f00,0x3f003f00,0xbf003f00,0x3f003f00,0xbf003f00,0x3f003f00,0xbf003f00,0x3f003f00,0xbf003f00,
0x3eff3f00,0xbd490000,0x3ea23eb5,0xbec6beb5,0x3ef53efb,0xbe15bdc8,0x3e713e8e,0xbee2bed5,0x3ee23eed,0xbe71be44,0x3e153e44,0xbef5beed,0x3ec63ed5,0xbea2be8e,0x3d493dc8,0xbeffbefb,
0x3efb3f00,0xbdc80000,0xbdc80000,0xbefbbf00,0x3ed53eed,0xbe8ebe44,0xbe8ebe44,0xbed5beed,0x3e8e3eb5,0xbed5beb5,0xbed5beb5,0xbe8ebeb5,0x3dc83e44,0xbefbbeed,0xbefbbeed,0xbdc8be44,
0x3ef53f00,0xbe150000,0xbee2beb5,0xbe71beb5,0x3ea23ed5,0xbec6be8e,0xbeffbefb,0x3d49bdc8,0x3d493e44,0xbeffbeed,0xbec6beed,0x3ea23e44,0xbe71bdc8,0xbee2befb,0xbe15be8e,0x3ef53ed5,
0x3eed3f00,0xbe440000,0xbeedbf00,0x3e440000,0x3e443eb5,0xbeedbeb5,0xbe44beb5,0x3eed3eb5,0xbe440000,0xbeedbf00,0x3e440000,0x3eed3f00,0xbeedbeb5,0xbe44beb5,0x3eed3eb5,0x3e443eb5,
0x3ee23f00,0xbe710000,0xbe15beb5,0x3ef53eb5,0x3d493e8e,0xbeffbed5,0x3ea23dc8,0x3ec63efb,0xbec6be44,0xbea2beed,0x3eff3eed,0xbd493e44,0xbef5befb,0x3e15bdc8,0x3e713ed5,0xbee2be8e,
0x3ed53f00,0xbe8e0000,0x3e8e0000,0x3ed53f00,0xbdc83e44,0xbefbbeed,0x3efb3eed,0xbdc83e44,0xbefbbeb5,0xbdc8beb5,0x3dc83eb5,0xbefbbeb5,0xbe8ebeed,0x3ed53e44,0xbed5be44,0xbe8ebeed,
0x3ec63f00,0xbea20000,0x3eff3eb5,0x3d493eb5,0xbe713dc8,0xbee2befb,0x3e153ed5,0xbef5be8e,0xbef5beed,0x3e15be44,0xbee2be44,0xbe71beed,0x3d49be8e,0x3eff3ed5,0xbea2befb,0x3ec63dc8,
0x3f00,0xbf000000,0x3f00,0xbf000000,0xbf00,0x3f000000,0xbf00,0x3f000000,0x3f00,0xbf000000,0x3f00,0xbf000000,0xbf00,0x3f000000,0xbf00,0x3f000000,
0xbd493f00,0xbeff0000,0xbec63eb5,0xbea2beb5,0x3e15befb,0x3ef53dc8,0x3ee2be8e,0x3e713ed5,0xbe713eed,0xbee2be44,0xbef53e44,0xbe15beed,0x3ea2bed5,0x3ec63e8e,0x3effbdc8,0x3d493efb,
0xbdc83f00,0xbefb0000,0xbefb0000,0x3dc8bf00,0x3e8ebeed,0x3ed53e44,0x3ed53e44,0xbe8e3eed,0xbed53eb5,0xbe8ebeb5,0xbe8ebeb5,0x3ed5beb5,0x3efbbe44,0x3dc83eed,0x3dc83eed,0xbefb3e44,
0xbe153f00,0xbef50000,0xbe71beb5,0x3ee2beb5,0x3ec6bed5,0x3ea23e8e,0xbd493efb,0xbeff3dc8,0xbeff3e44,0xbd49beed,0x3ea2beed,0x3ec63e44,0x3ee23dc8,0xbe713efb,0xbef53e8e,0xbe15bed5,
0xbe443f00,0xbeed0000,0x3e44bf00,0x3eed0000,0x3eedbeb5,0x3e443eb5,0xbeed3eb5,0xbe44beb5,0xbeed0000,0x3e44bf00,0x3eed0000,0xbe443f00,0x3e443eb5,0xbeed3eb5,0xbe44beb5,0x3eedbeb5,
0xbe713f00,0xbee20000,0x3ef5beb5,0x3e153eb5,0x3effbe8e,0x3d493ed5,0xbec6bdc8,0x3ea2befb,0xbea2be44,0x3ec6beed,0xbd493eed,0xbeff3e44,0xbe153efb,0xbef53dc8,0x3ee2bed5,0x3e713e8e,
0xbe8e3f00,0xbed50000,0x3ed50000,0xbe8e3f00,0x3efbbe44,0xbdc83eed,0x3dc8beed,0x3efbbe44,0xbdc8beb5,0x3efbbeb5,0xbefb3eb5,0xbdc8beb5,0xbed53eed,0xbe8ebe44,0x3e8e3e44,0xbed53eed,
0xbea23f00,0xbec60000,0x3d493eb5,0xbeff3eb5,0x3ee2bdc8,0xbe713efb,0x3ef5bed5,0x3e153e8e,0x3e15beed,0x3ef5be44,0xbe71be44,0x3ee2beed,0xbeff3e8e,0x3d49bed5,0xbec63efb,0xbea2bdc8,
0x3eb53f00,0xbeb50000,0x3eb53f00,0xbeb50000,0xbeb50000,0xbeb5bf00,0xbeb50000,0xbeb5bf00,0xbeb5bf00,0x3eb50000,0xbeb5bf00,0x3eb50000,0x3eb50000,0x3eb53f00,0x3eb50000,0x3eb53f00,
0xbeff3f00,0x3d490000,0xbea23eb5,0x3ec6beb5,0xbef53efb,0x3e15bdc8,0xbe713e8e,0x3ee2bed5,0xbee23eed,0x3e71be44,0xbe153e44,0x3ef5beed,0xbec63ed5,0x3ea2be8e,0xbd493dc8,0x3effbefb,
0xbefb3f00,0x3dc80000,0x3dc80000,0x3efbbf00,0xbed53eed,0x3e8ebe44,0x3e8ebe44,0x3ed5beed,0xbe8e3eb5,0x3ed5beb5,0x3ed5beb5,0x3e8ebeb5,0xbdc83e44,0x3efbbeed,0x3efbbeed,0x3dc8be44,
0xbef53f00,0x3e150000,0x3ee2beb5,0x3e71beb5,0xbea23ed5,0x3ec6be8e,0x3effbefb,0xbd49bdc8,0xbd493e44,0x3effbeed,0x3ec6beed,0xbea23e44,0x3e71bdc8,0x3ee2befb,0x3e15be8e,0xbef53ed5,
0xbeed3f00,0x3e440000,0x3eedbf00,0xbe440000,0xbe443eb5,0x3eedbeb5,0x3e44beb5,0xbeed3eb5,0x3e440000,0x3eedbf00,0xbe440000,0xbeed3f00,0x3eedbeb5,0x3e44beb5,0xbeed3eb5,0xbe443eb5,
0xbee23f00,0x3e710000,0x3e15beb5,0xbef53eb5,0xbd493e8e,0x3effbed5,0xbea23dc8,0xbec63efb,0x3ec6be44,0x3ea2beed,0xbeff3eed,0x3d493e44,0x3ef5befb,0xbe15bdc8,0xbe713ed5,0x3ee2be8e,
0xbed53f00,0x3e8e0000,0xbe8e0000,0xbed53f00,0x3dc83e44,0x3efbbeed,0xbefb3eed,0x3dc83e44,0x3efbbeb5,0x3dc8beb5,0xbdc83eb5,0x3efbbeb5,0x3e8ebeed,0xbed53e44,0x3ed5be44,0x3e8ebeed,
0xbec63f00,0x3ea20000,0xbeff3eb5,0xbd493eb5,0x3e713dc8,0x3ee2befb,0xbe153ed5,0x3ef5be8e,0x3ef5beed,0xbe15be44,0x3ee2be44,0x3e71beed,0xbd49be8e,0xbeff3ed5,0x3ea2befb,0xbec63dc8,
0xbeb53f00,0xbeb50000,0xbeb53f00,0xbeb50000,0x3eb50000,0xbeb53f00,0x3eb50000,0xbeb53f00,0x3eb5bf00,0x3eb50000,0x3eb5bf00,0x3eb50000,0xbeb50000,0x3eb5bf00,0xbeb50000,0x3eb5bf00,
0x3d493f00,0x3eff0000,0x3ec63eb5,0x3ea2beb5,0xbe15befb,0xbef53dc8,0xbee2be8e,0xbe713ed5,0x3e713eed,0x3ee2be44,0x3ef53e44,0x3e15beed,0xbea2bed5,0xbec63e8e,0xbeffbdc8,0xbd493efb,
0x3dc83f00,0x3efb0000,0x3efb0000,0xbdc8bf00,0xbe8ebeed,0xbed53e44,0xbed53e44,0x3e8e3eed,0x3ed53eb5,0x3e8ebeb5,0x3e8ebeb5,0xbed5beb5,0xbefbbe44,0xbdc83eed,0xbdc83eed,0x3efb3e44,
0x3e153f00,0x3ef50000,0x3e71beb5,0xbee2beb5,0xbec6bed5,0xbea23e8e,0x3d493efb,0x3eff3dc8,0x3eff3e44,0x3d49beed,0xbea2beed,0xbec63e44,0xbee23dc8,0x3e713efb,0x3ef53e8e,0x3e15bed5,
0x3e443f00,0x3eed0000,0xbe44bf00,0xbeed0000,0xbeedbeb5,0xbe443eb5,0x3eed3eb5,0x3e44beb5,0x3eed0000,0xbe44bf00,0xbeed0000,0x3e443f00,0xbe443eb5,0x3eed3eb5,0x3e44beb5,0xbeedbeb5,
0x3e713f00,0x3ee20000,0xbef5beb5,0xbe153eb5,0xbeffbe8e,0xbd493ed5,0x3ec6bdc8,0xbea2befb,0x3ea2be44,0xbec6beed,0x3d493eed,0x3eff3e44,0x3e153efb,0x3ef53dc8,0xbee2bed5,0xbe713e8e,
0x3e8e3f00,0x3ed50000,0xbed50000,0x3e8e3f00,0xbefbbe44,0x3dc83eed,0xbdc8beed,0xbefbbe44,0x3dc8beb5,0xbefbbeb5,0x3efb3eb5,0x3dc8beb5,0x3ed53eed,0x3e8ebe44,0xbe8e3e44,0x3ed53eed,
0x3ea23f00,0x3ec60000,0xbd493eb5,0x3eff3eb5,0xbee2bdc8,0x3e713efb,0xbef5bed5,0xbe153e8e,0xbe15beed,0xbef5be44,0x3e71be44,0xbee2beed,0x3eff3e8e,0xbd49bed5,0x3ec63efb,0x3ea2bdc8,
0x3f003f00,0xbf003f00,0x3f003f00,0xbf003f00,0x3f003f00,0xbf003f00,0x3f003f00,0xbf003f00,0x3f003f00,0xbf003f00,0x3f003f00,0xbf003f00,0x3f003f00,0xbf003f00,0x3f003f00,0xbf003f00,
0xbd490000,0xbeffbf00,0xbec6beb5,0xbea2beb5,0xbe15bdc8,0xbef5befb,0xbee2bed5,0xbe71be8e,0xbe71be44,0xbee2beed,0xbef5beed,0xbe15be44,0xbea2be8e,0xbec6bed5,0xbeffbefb,0xbd49bdc8,
0xbefbbf00,0x3dc80000,0x3dc80000,0x3efb3f00,0xbed5beed,0x3e8e3e44,0x3e8e3e44,0x3ed53eed,0xbe8ebeb5,0x3ed53eb5,0x3ed53eb5,0x3e8e3eb5,0xbdc8be44,0x3efb3eed,0x3efb3eed,0x3dc83e44,
0x3e150000,0x3ef53f00,0x3e713eb5,0xbee2beb5,0x3ec63e8e,0x3ea23ed5,0xbd493dc8,0xbeffbefb,0x3eff3eed,0x3d493e44,0xbea2be44,0xbec6beed,0x3ee23efb,0xbe71bdc8,0xbef5bed5,0xbe15be8e,
0x3eed3f00,0xbe440000,0xbeedbf00,0x3e440000,0x3e443eb5,0xbeedbeb5,0xbe44beb5,0x3eed3eb5,0xbe440000,0xbeedbf00,0x3e440000,0x3eed3f00,0xbeedbeb5,0xbe44beb5,0x3eed3eb5,0x3e443eb5,
0xbe710000,0xbee2bf00,0x3ef53eb5,0x3e153eb5,0xbeffbed5,0xbd49be8e,0x3ec63efb,0xbea2bdc8,0xbea2beed,0x3ec63e44,0xbd493e44,0xbeffbeed,0x3e15bdc8,0x3ef53efb,0xbee2be8e,0xbe71bed5,
0xbed5bf00,0x3e8e0000,0xbe8e0000,0xbed5bf00,0x3dc8be44,0x3efb3eed,0xbefbbeed,0x3dc8be44,0x3efb3eb5,0x3dc83eb5,0xbdc8beb5,0x3efb3eb5,0x3e8e3eed,0xbed5be44,0x3ed53e44,0x3e8e3eed,
0x3ea20000,0x3ec63f00,0xbd49beb5,0x3eff3eb5,0x3ee23efb,0xbe713dc8,0x3ef53e8e,0x3e153ed5,0xbe153e44,0xbef5beed,0x3e713eed,0xbee2be44,0xbeffbed5,0x3d49be8e,0xbec6bdc8,0xbea2befb,
0x3f00,0xbf000000,0x3f00,0xbf000000,0xbf00,0x3f000000,0xbf00,0x3f000000,0x3f00,0xbf000000,0x3f00,0xbf000000,0xbf00,0x3f000000,0xbf00,0x3f000000,
0xbeff0000,0x3d49bf00,0xbea2beb5,0x3ec6beb5,0x3ef53dc8,0xbe153efb,0x3e713ed5,0xbee23e8e,0xbee2be44,0x3e71beed,0xbe15beed,0x3ef5be44,0x3ec63e8e,0xbea23ed5,0x3d493efb,0xbeff3dc8,
0x3dc8bf00,0x3efb0000,0x3efb0000,0xbdc83f00,0xbe8e3eed,0xbed5be44,0xbed5be44,0x3e8ebeed,0x3ed5beb5,0x3e8e3eb5,0x3e8e3eb5,0xbed53eb5,0xbefb3e44,0xbdc8beed,0xbdc8beed,0x3efbbe44,
0x3ef50000,0xbe153f00,0xbee23eb5,0xbe71beb5,0xbea2be8e,0x3ec6bed5,0x3effbdc8,0xbd493efb,0x3d493eed,0xbeff3e44,0xbec6be44,0x3ea2beed,0x3e71befb,0x3ee23dc8,0x3e153ed5,0xbef53e8e,
0xbe443f00,0xbeed0000,0x3e44bf00,0x3eed0000,0x3eedbeb5,0x3e443eb5,0xbeed3eb5,0xbe44beb5,0xbeed0000,0x3e44bf00,0x3eed0000,0xbe443f00,0x3e443eb5,0xbeed3eb5,0xbe44beb5,0x3eedbeb5,
0xbee20000,0x3e71bf00,0x3e153eb5,0xbef53eb5,0x3d493ed5,0xbeff3e8e,0x3ea2befb,0x3ec63dc8,0x3ec6beed,0x3ea23e44,0xbeff3e44,0x3d49beed,0xbef53dc8,0x3e15befb,0x3e713e8e,0xbee23ed5,
0x3e8ebf00,0x3ed50000,0xbed50000,0x3e8ebf00,0xbefb3e44,0x3dc8beed,0xbdc83eed,0xbefb3e44,0x3dc83eb5,0xbefb3eb5,0x3efbbeb5,0x3dc83eb5,0x3ed5beed,0x3e8e3e44,0xbe8ebe44,0x3ed5beed,
0x3ec60000,0xbea23f00,0x3effbeb5,0x3d493eb5,0x3e71befb,0x3ee2bdc8,0xbe15be8e,0x3ef5bed5,0xbef53e44,0x3e15beed,0xbee23eed,0xbe71be44,0xbd493ed5,0xbeff3e8e,0x3ea23dc8,0xbec63efb,
0x3eb53f00,0xbeb50000,0x3eb53f00,0xbeb50000,0xbeb50000,0xbeb5bf00,0xbeb50000,0xbeb5bf00,0xbeb5bf00,0x3eb50000,0xbeb5bf00,0x3eb50000,0x3eb50000,0x3eb53f00,0x3eb50000,0x3eb53f00,
0x3d490000,0x3effbf00,0x3ec6beb5,0x3ea2beb5,0x3e15bdc8,0x3ef5befb,0x3ee2bed5,0x3e71be8e,0x3e71be44,0x3ee2beed,0x3ef5beed,0x3e15be44,0x3ea2be8e,0x3ec6bed5,0x3effbefb,0x3d49bdc8,
0x3efbbf00,0xbdc80000,0xbdc80000,0xbefb3f00,0x3ed5beed,0xbe8e3e44,0xbe8e3e44,0xbed53eed,0x3e8ebeb5,0xbed53eb5,0xbed53eb5,0xbe8e3eb5,0x3dc8be44,0xbefb3eed,0xbefb3eed,0xbdc83e44,
0xbe150000,0xbef53f00,0xbe713eb5,0x3ee2beb5,0xbec63e8e,0xbea23ed5,0x3d493dc8,0x3effbefb,0xbeff3eed,0xbd493e44,0x3ea2be44,0x3ec6beed,0xbee23efb,0x3e71bdc8,0x3ef5bed5,0x3e15be8e,
0xbeed3f00,0x3e440000,0x3eedbf00,0xbe440000,0xbe443eb5,0x3eedbeb5,0x3e44beb5,0xbeed3eb5,0x3e440000,0x3eedbf00,0xbe440000,0xbeed3f00,0x3eedbeb5,0x3e44beb5,0xbeed3eb5,0xbe443eb5,
0x3e710000,0x3ee2bf00,0xbef53eb5,0xbe153eb5,0x3effbed5,0x3d49be8e,0xbec63efb,0x3ea2bdc8,0x3ea2beed,0xbec63e44,0x3d493e44,0x3effbeed,0xbe15bdc8,0xbef53efb,0x3ee2be8e,0x3e71bed5,
0x3ed5bf00,0xbe8e0000,0x3e8e0000,0x3ed5bf00,0xbdc8be44,0xbefb3eed,0x3efbbeed,0xbdc8be44,0xbefb3eb5,0xbdc83eb5,0x3dc8beb5,0xbefb3eb5,0xbe8e3eed,0x3ed5be44,0xbed53e44,0xbe8e3eed,
0xbea20000,0xbec63f00,0x3d49beb5,0xbeff3eb5,0xbee23efb,0x3e713dc8,0xbef53e8e,0xbe153ed5,0x3e153e44,0x3ef5beed,0xbe713eed,0x3ee2be44,0x3effbed5,0xbd49be8e,0x3ec6bdc8,0x3ea2befb,
0xbeb53f00,0xbeb50000,0xbeb53f00,0xbeb50000,0x3eb50000,0xbeb53f00,0x3eb50000,0xbeb53f00,0x3eb5bf00,0x3eb50000,0x3eb5bf00,0x3eb50000,0xbeb50000,0x3eb5bf00,0xbeb50000,0x3eb5bf00,
0x3eff0000,0xbd49bf00,0x3ea2beb5,0xbec6beb5,0xbef53dc8,0x3e153efb,0xbe713ed5,0x3ee23e8e,0x3ee2be44,0xbe71beed,0x3e15beed,0xbef5be44,0xbec63e8e,0x3ea23ed5,0xbd493efb,0x3eff3dc8,
0xbdc8bf00,0xbefb0000,0xbefb0000,0x3dc83f00,0x3e8e3eed,0x3ed5be44,0x3ed5be44,0xbe8ebeed,0xbed5beb5,0xbe8e3eb5,0xbe8e3eb5,0x3ed53eb5,0x3efb3e44,0x3dc8beed,0x3dc8beed,0xbefbbe44,
0xbef50000,0x3e153f00,0x3ee23eb5,0x3e71beb5,0x3ea2be8e,0xbec6bed5,0xbeffbdc8,0x3d493efb,0xbd493eed,0x3eff3e44,0x3ec6be44,0xbea2beed,0xbe71befb,0xbee23dc8,0xbe153ed5,0x3ef53e8e,
0x3e443f00,0x3eed0000,0xbe44bf00,0xbeed0000,0xbeedbeb5,0xbe443eb5,0x3eed3eb5,0x3e44beb5,0x3eed0000,0xbe44bf00,0xbeed0000,0x3e443f00,0xbe443eb5,0x3eed3eb5,0x3e44beb5,0xbeedbeb5,
0x3ee20000,0xbe71bf00,0xbe153eb5,0x3ef53eb5,0xbd493ed5,0x3eff3e8e,0xbea2befb,0xbec63dc8,0xbec6beed,0xbea23e44,0x3eff3e44,0xbd49beed,0x3ef53dc8,0xbe15befb,0xbe713e8e,0x3ee23ed5,
0xbe8ebf00,0xbed50000,0x3ed50000,0xbe8ebf00,0x3efb3e44,0xbdc8beed,0x3dc83eed,0x3efb3e44,0xbdc83eb5,0x3efb3eb5,0xbefbbeb5,0xbdc83eb5,0xbed5beed,0xbe8e3e44,0x3e8ebe44,0xbed5beed,
0xbec60000,0x3ea23f00,0xbeffbeb5,0xbd493eb5,0xbe71befb,0xbee2bdc8,0x3e15be8e,0xbef5bed5,0x3ef53e44,0xbe15beed,0x3ee23eed,0x3e71be44,0x3d493ed5,0x3eff3e8e,0xbea23dc8,0x3ec63efb,
0x3f003f00,0xbf003f00,0x3f003f00,0xbf003f00,0x3f003f00,0xbf003f00,0x3f003f00,0xbf003f00,0x3f003f00,0xbf003f00,0x3f003f00,0xbf003f00,0x3f003f00,0xbf003f00,0x3f003f00,0xbf003f00,
0xbeffbf00,0x3d490000,0xbea2beb5,0x3ec63eb5,0xbef5befb,0x3e153dc8,0xbe71be8e,0x3ee23ed5,0xbee2beed,0x3e713e44,0xbe15be44,0x3ef53eed,0xbec6bed5,0x3ea23e8e,0xbd49bdc8,0x3eff3efb,
0x3efb3f00,0xbdc80000,0xbdc80000,0xbefbbf00,0x3ed53eed,0xbe8ebe44,0xbe8ebe44,0xbed5beed,0x3e8e3eb5,0xbed5beb5,0xbed5beb5,0xbe8ebeb5,0x3dc83e44,0xbefbbeed,0xbefbbeed,0xbdc8be44,
0xbef5bf00,0x3e150000,0x3ee23eb5,0x3e713eb5,0xbea2bed5,0x3ec63e8e,0x3eff3efb,0xbd493dc8,0xbd49be44,0x3eff3eed,0x3ec63eed,0xbea2be44,0x3e713dc8,0x3ee23efb,0x3e153e8e,0xbef5bed5,
0x3eed3f00,0xbe440000,0xbeedbf00,0x3e440000,0x3e443eb5,0xbeedbeb5,0xbe44beb5,0x3eed3eb5,0xbe440000,0xbeedbf00,0x3e440000,0x3eed3f00,0xbeedbeb5,0xbe44beb5,0x3eed3eb5,0x3e443eb5,
0xbee2bf00,0x3e710000,0x3e153eb5,0xbef5beb5,0xbd49be8e,0x3eff3ed5,0xbea2bdc8,0xbec6befb,0x3ec63e44,0x3ea23eed,0xbeffbeed,0x3d49be44,0x3ef53efb,0xbe153dc8,0xbe71bed5,0x3ee23e8e,
0x3ed53f00,0xbe8e0000,0x3e8e0000,0x3ed53f00,0xbdc83e44,0xbefbbeed,0x3efb3eed,0xbdc83e44,0xbefbbeb5,0xbdc8beb5,0x3dc83eb5,0xbefbbeb5,0xbe8ebeed,0x3ed53e44,0xbed5be44,0xbe8ebeed,
0xbec6bf00,0x3ea20000,0xbeffbeb5,0xbd49beb5,0x3e71bdc8,0x3ee23efb,0xbe15bed5,0x3ef53e8e,0x3ef53eed,0xbe153e44,0x3ee23e44,0x3e713eed,0xbd493e8e,0xbeffbed5,0x3ea23efb,0xbec6bdc8,
0x3f00,0xbf000000,0x3f00,0xbf000000,0xbf00,0x3f000000,0xbf00,0x3f000000,0x3f00,0xbf000000,0x3f00,0xbf000000,0xbf00,0x3f000000,0xbf00,0x3f000000,
0x3d49bf00,0x3eff0000,0x3ec6beb5,0x3ea23eb5,0xbe153efb,0xbef5bdc8,0xbee23e8e,0xbe71bed5,0x3e71beed,0x3ee23e44,0x3ef5be44,0x3e153eed,0xbea23ed5,0xbec6be8e,0xbeff3dc8,0xbd49befb,
0xbdc83f00,0xbefb0000,0xbefb0000,0x3dc8bf00,0x3e8ebeed,0x3ed53e44,0x3ed53e44,0xbe8e3eed,0xbed53eb5,0xbe8ebeb5,0xbe8ebeb5,0x3ed5beb5,0x3efbbe44,0x3dc83eed,0x3dc83eed,0xbefb3e44,
0x3e15bf00,0x3ef50000,0x3e713eb5,0xbee23eb5,0xbec63ed5,0xbea2be8e,0x3d49befb,0x3effbdc8,0x3effbe44,0x3d493eed,0xbea23eed,0xbec6be44,0xbee2bdc8,0x3e71befb,0x3ef5be8e,0x3e153ed5,
0xbe443f00,0xbeed0000,0x3e44bf00,0x3eed0000,0x3eedbeb5,0x3e443eb5,0xbeed3eb5,0xbe44beb5,0xbeed0000,0x3e44bf00,0x3eed0000,0xbe443f00,0x3e443eb5,0xbeed3eb5,0xbe44beb5,0x3eedbeb5,
0x3e71bf00,0x3ee20000,0xbef53eb5,0xbe15beb5,0xbeff3e8e,0xbd49bed5,0x3ec63dc8,0xbea23efb,0x3ea23e44,0xbec63eed,0x3d49beed,0x3effbe44,0x3e15befb,0x3ef5bdc8,0xbee23ed5,0xbe71be8e,
0xbe8e3f00,0xbed50000,0x3ed50000,0xbe8e3f00,0x3efbbe44,0xbdc83eed,0x3dc8beed,0x3efbbe44,0xbdc8beb5,0x3efbbeb5,0xbefb3eb5,0xbdc8beb5,0xbed53eed,0xbe8ebe44,0x3e8e3e44,0xbed53eed,
0x3ea2bf00,0x3ec60000,0xbd49beb5,0x3effbeb5,0xbee23dc8,0x3e71befb,0xbef53ed5,0xbe15be8e,0xbe153eed,0xbef53e44,0x3e713e44,0xbee23eed,0x3effbe8e,0xbd493ed5,0x3ec6befb,0x3ea23dc8,
0x3eb53f00,0xbeb50000,0x3eb53f00,0xbeb50000,0xbeb50000,0xbeb5bf00,0xbeb50000,0xbeb5bf00,0xbeb5bf00,0x3eb50000,0xbeb5bf00,0x3eb50000,0x3eb50000,0x3eb53f00,0x3eb50000,0x3eb53f00,
0x3effbf00,0xbd490000,0x3ea2beb5,0xbec63eb5,0x3ef5befb,0xbe153dc8,0x3e71be8e,0xbee23ed5,0x3ee2beed,0xbe713e44,0x3e15be44,0xbef53eed,0x3ec6bed5,0xbea23e8e,0x3d49bdc8,0xbeff3efb,
0xbefb3f00,0x3dc80000,0x3dc80000,0x3efbbf00,0xbed53eed,0x3e8ebe44,0x3e8ebe44,0x3ed5beed,0xbe8e3eb5,0x3ed5beb5,0x3ed5beb5,0x3e8ebeb5,0xbdc83e44,0x3efbbeed,0x3efbbeed,0x3dc8be44,
0x3ef5bf00,0xbe150000,0xbee23eb5,0xbe713eb5,0x3ea2bed5,0xbec63e8e,0xbeff3efb,0x3d493dc8,0x3d49be44,0xbeff3eed,0xbec63eed,0x3ea2be44,0xbe713dc8,0xbee23efb,0xbe153e8e,0x3ef5bed5,
0xbeed3f00,0x3e440000,0x3eedbf00,0xbe440000,0xbe443eb5,0x3eedbeb5,0x3e44beb5,0xbeed3eb5,0x3e440000,0x3eedbf00,0xbe440000,0xbeed3f00,0x3eedbeb5,0x3e44beb5,0xbeed3eb5,0xbe443eb5,
0x3ee2bf00,0xbe710000,0xbe153eb5,0x3ef5beb5,0x3d49be8e,0xbeff3ed5,0x3ea2bdc8,0x3ec6befb,0xbec63e44,0xbea23eed,0x3effbeed,0xbd49be44,0xbef53efb,0x3e153dc8,0x3e71bed5,0xbee23e8e,
0xbed53f00,0x3e8e0000,0xbe8e0000,0xbed53f00,0x3dc83e44,0x3efbbeed,0xbefb3eed,0x3dc83e44,0x3efbbeb5,0x3dc8beb5,0xbdc83eb5,0x3efbbeb5,0x3e8ebeed,0xbed53e44,0x3ed5be44,0x3e8ebeed,
0x3ec6bf00,0xbea20000,0x3effbeb5,0x3d49beb5,0xbe71bdc8,0xbee23efb,0x3e15bed5,0xbef53e8e,0xbef53eed,0x3e153e44,0xbee23e44,0xbe713eed,0x3d493e8e,0x3effbed5,0xbea23efb,0x3ec6bdc8,
0xbeb53f00,0xbeb50000,0xbeb53f00,0xbeb50000,0x3eb50000,0xbeb53f00,0x3eb50000,0xbeb53f00,0x3eb5bf00,0x3eb50000,0x3eb5bf00,0x3eb50000,0xbeb50000,0x3eb5bf00,0xbeb50000,0x3eb5bf00,
0xbd49bf00,0xbeff0000,0xbec6beb5,0xbea23eb5,0x3e153efb,0x3ef5bdc8,0x3ee23e8e,0x3e71bed5,0xbe71beed,0xbee23e44,0xbef5be44,0xbe153eed,0x3ea23ed5,0x3ec6be8e,0x3eff3dc8,0x3d49befb,
0x3dc83f00,0x3efb0000,0x3efb0000,0xbdc8bf00,0xbe8ebeed,0xbed53e44,0xbed53e44,0x3e8e3eed,0x3ed53eb5,0x3e8ebeb5,0x3e8ebeb5,0xbed5beb5,0xbefbbe44,0xbdc83eed,0xbdc83eed,0x3efb3e44,
0xbe15bf00,0xbef50000,0xbe713eb5,0x3ee23eb5,0x3ec63ed5,0x3ea2be8e,0xbd49befb,0xbeffbdc8,0xbeffbe44,0xbd493eed,0x3ea23eed,0x3ec6be44,0x3ee2bdc8,0xbe71befb,0xbef5be8e,0xbe153ed5,
0x3e443f00,0x3eed0000,0xbe44bf00,0xbeed0000,0xbeedbeb5,0xbe443eb5,0x3eed3eb5,0x3e44beb5,0x3eed0000,0xbe44bf00,0xbeed0000,0x3e443f00,0xbe443eb5,0x3eed3eb5,0x3e44beb5,0xbeedbeb5,
0xbe71bf00,0xbee20000,0x3ef53eb5,0x3e15beb5,0x3eff3e8e,0x3d49bed5,0xbec63dc8,0x3ea23efb,0xbea23e44,0x3ec63eed,0xbd49beed,0xbeffbe44,0xbe15befb,0xbef5bdc8,0x3ee23ed5,0x3e71be8e,
0x3e8e3f00,0x3ed50000,0xbed50000,0x3e8e3f00,0xbefbbe44,0x3dc83eed,0xbdc8beed,0xbefbbe44,0x3dc8beb5,0xbefbbeb5,0x3efb3eb5,0x3dc8beb5,0x3ed53eed,0x3e8ebe44,0xbe8e3e44,0x3ed53eed,
0xbea2bf00,0xbec60000,0x3d49beb5,0xbeffbeb5,0x3ee23dc8,0xbe71befb,0x3ef53ed5,0x3e15be8e,0x3e153eed,0x3ef53e44,0xbe713e44,0x3ee23eed,0xbeffbe8e,0x3d493ed5,0xbec6befb,0xbea23dc8,
0x3f003f00,0xbf003f00,0x3f003f00,0xbf003f00,0x3f003f00,0xbf003f00,0x3f003f00,0xbf003f00,0x3f003f00,0xbf003f00,0x3f003f00,0xbf003f00,0x3f003f00,0xbf003f00,0x3f003f00,0xbf003f00,
0x3d490000,0x3eff3f00,0x3ec63eb5,0x3ea23eb5,0x3e153dc8,0x3ef53efb,0x3ee23ed5,0x3e713e8e,0x3e713e44,0x3ee23eed,0x3ef53eed,0x3e153e44,0x3ea23e8e,0x3ec63ed5,0x3eff3efb,0x3d493dc8,
0xbefbbf00,0x3dc80000,0x3dc80000,0x3efb3f00,0xbed5beed,0x3e8e3e44,0x3e8e3e44,0x3ed53eed,0xbe8ebeb5,0x3ed53eb5,0x3ed53eb5,0x3e8e3eb5,0xbdc8be44,0x3efb3eed,0x3efb3eed,0x3dc83e44,
0xbe150000,0xbef5bf00,0xbe71beb5,0x3ee23eb5,0xbec6be8e,0xbea2bed5,0x3d49bdc8,0x3eff3efb,0xbeffbeed,0xbd49be44,0x3ea23e44,0x3ec63eed,0xbee2befb,0x3e713dc8,0x3ef53ed5,0x3e153e8e,
0x3eed3f00,0xbe440000,0xbeedbf00,0x3e440000,0x3e443eb5,0xbeedbeb5,0xbe44beb5,0x3eed3eb5,0xbe440000,0xbeedbf00,0x3e440000,0x3eed3f00,0xbeedbeb5,0xbe44beb5,0x3eed3eb5,0x3e443eb5,
0x3e710000,0x3ee23f00,0xbef5beb5,0xbe15beb5,0x3eff3ed5,0x3d493e8e,0xbec6befb,0x3ea23dc8,0x3ea23eed,0xbec6be44,0x3d49be44,0x3eff3eed,0xbe153dc8,0xbef5befb,0x3ee23e8e,0x3e713ed5,
0xbed5bf00,0x3e8e0000,0xbe8e0000,0xbed5bf00,0x3dc8be44,0x3efb3eed,0xbefbbeed,0x3dc8be44,0x3efb3eb5,0x3dc83eb5,0xbdc8beb5,0x3efb3eb5,0x3e8e3eed,0xbed5be44,0x3ed53e44,0x3e8e3eed,
0xbea20000,0xbec6bf00,0x3d493eb5,0xbeffbeb5,0xbee2befb,0x3e71bdc8,0xbef5be8e,0xbe15bed5,0x3e15be44,0x3ef53eed,0xbe71beed,0x3ee23e44,0x3eff3ed5,0xbd493e8e,0x3ec63dc8,0x3ea23efb,
0x3f00,0xbf000000,0x3f00,0xbf000000,0xbf00,0x3f000000,0xbf00,0x3f000000,0x3f00,0xbf000000,0x3f00,0xbf000000,0xbf00,0x3f000000,0xbf00,0x3f000000,
0x3eff0000,0xbd493f00,0x3ea23eb5,0xbec63eb5,0xbef5bdc8,0x3e15befb,0xbe71bed5,0x3ee2be8e,0x3ee23e44,0xbe713eed,0x3e153eed,0xbef53e44,0xbec6be8e,0x3ea2bed5,0xbd49befb,0x3effbdc8,
0x3dc8bf00,0x3efb0000,0x3efb0000,0xbdc83f00,0xbe8e3eed,0xbed5be44,0xbed5be44,0x3e8ebeed,0x3ed5beb5,0x3e8e3eb5,0x3e8e3eb5,0xbed53eb5,0xbefb3e44,0xbdc8beed,0xbdc8beed,0x3efbbe44,
0xbef50000,0x3e15bf00,0x3ee2beb5,0x3e713eb5,0x3ea23e8e,0xbec63ed5,0xbeff3dc8,0x3d49befb,0xbd49beed,0x3effbe44,0x3ec63e44,0xbea23eed,0xbe713efb,0xbee2bdc8,0xbe15bed5,0x3ef5be8e,
0xbe443f00,0xbeed0000,0x3e44bf00,0x3eed0000,0x3eedbeb5,0x3e443eb5,0xbeed3eb5,0xbe44beb5,0xbeed0000,0x3e44bf00,0x3eed0000,0xbe443f00,0x3e443eb5,0xbeed3eb5,0xbe44beb5,0x3eedbeb5,
0x3ee20000,0xbe713f00,0xbe15beb5,0x3ef5beb5,0xbd49bed5,0x3effbe8e,0xbea23efb,0xbec6bdc8,0xbec63eed,0xbea2be44,0x3effbe44,0xbd493eed,0x3ef5bdc8,0xbe153efb,0xbe71be8e,0x3ee2bed5,
0x3e8ebf00,0x3ed50000,0xbed50000,0x3e8ebf00,0xbefb3e44,0x3dc8beed,0xbdc83eed,0xbefb3e44,0x3dc83eb5,0xbefb3eb5,0x3efbbeb5,0x3dc83eb5,0x3ed5beed,0x3e8e3e44,0xbe8ebe44,0x3ed5beed,
0xbec60000,0x3ea2bf00,0xbeff3eb5,0xbd49beb5,0xbe713efb,0xbee23dc8,0x3e153e8e,0xbef53ed5,0x3ef5be44,0xbe153eed,0x3ee2beed,0x3e713e44,0x3d49bed5,0x3effbe8e,0xbea2bdc8,0x3ec6befb,
0x3eb53f00,0xbeb50000,0x3eb53f00,0xbeb50000,0xbeb50000,0xbeb5bf00,0xbeb50000,0xbeb5bf00,0xbeb5bf00,0x3eb50000,0xbeb5bf00,0x3eb50000,0x3eb50000,0x3eb53f00,0x3eb50000,0x3eb53f00,
0xbd490000,0xbeff3f00,0xbec63eb5,0xbea23eb5,0xbe153dc8,0xbef53efb,0xbee23ed5,0xbe713e8e,0xbe713e44,0xbee23eed,0xbef53eed,0xbe153e44,0xbea23e8e,0xbec63ed5,0xbeff3efb,0xbd493dc8,
0x3efbbf00,0xbdc80000,0xbdc80000,0xbefb3f00,0x3ed5beed,0xbe8e3e44,0xbe8e3e44,0xbed53eed,0x3e8ebeb5,0xbed53eb5,0xbed53eb5,0xbe8e3eb5,0x3dc8be44,0xbefb3eed,0xbefb3eed,0xbdc83e44,
0x3e150000,0x3ef5bf00,0x3e71beb5,0xbee23eb5,0x3ec6be8e,0x3ea2bed5,0xbd49bdc8,0xbeff3efb,0x3effbeed,0x3d49be44,0xbea23e44,0xbec63eed,0x3ee2befb,0xbe713dc8,0xbef53ed5,0xbe153e8e,
0xbeed3f00,0x3e440000,0x3eedbf00,0xbe440000,0xbe443eb5,0x3eedbeb5,0x3e44beb5,0xbeed3eb5,0x3e440000,0x3eedbf00,0xbe440000,0xbeed3f00,0x3eedbeb5,0x3e44beb5,0xbeed3eb5,0xbe443eb5,
0xbe710000,0xbee23f00,0x3ef5beb5,0x3e15beb5,0xbeff3ed5,0xbd493e8e,0x3ec6befb,0xbea23dc8,0xbea23eed,0x3ec6be44,0xbd49be44,0xbeff3eed,0x3e153dc8,0x3ef5befb,0xbee23e8e,0xbe713ed5,
0x3ed5bf00,0xbe8e0000,0x3e8e0000,0x3ed5bf00,0xbdc8be44,0xbefb3eed,0x3efbbeed,0xbdc8be44,0xbefb3eb5,0xbdc83eb5,0x3dc8beb5,0xbefb3eb5,0xbe8e3eed,0x3ed5be44,0xbed53e44,0xbe8e3eed,
0x3ea20000,0x3ec6bf00,0xbd493eb5,0x3effbeb5,0x3ee2befb,0xbe71bdc8,0x3ef5be8e,0x3e15bed5,0xbe15be44,0xbef53eed,0x3e71beed,0xbee23e44,0xbeff3ed5,0x3d493e8e,0xbec63dc8,0xbea23efb,
0xbeb53f00,0xbeb50000,0xbeb53f00,0xbeb50000,0x3eb50000,0xbeb53f00,0x3eb50000,0xbeb53f00,0x3eb5bf00,0x3eb50000,0x3eb5bf00,0x3eb50000,0xbeb50000,0x3eb5bf00,0xbeb50000,0x3eb5bf00,
0xbeff0000,0x3d493f00,0xbea23eb5,0x3ec63eb5,0x3ef5bdc8,0xbe15befb,0x3e71bed5,0xbee2be8e,0xbee23e44,0x3e713eed,0xbe153eed,0x3ef53e44,0x3ec6be8e,0xbea2bed5,0x3d49befb,0xbeffbdc8,
0xbdc8bf00,0xbefb0000,0xbefb0000,0x3dc83f00,0x3e8e3eed,0x3ed5be44,0x3ed5be44,0xbe8ebeed,0xbed5beb5,0xbe8e3eb5,0xbe8e3eb5,0x3ed53eb5,0x3efb3e44,0x3dc8beed,0x3dc8beed,0xbefbbe44,
0x3ef50000,0xbe15bf00,0xbee2beb5,0xbe713eb5,0xbea23e8e,0x3ec63ed5,0x3eff3dc8,0xbd49befb,0x3d49beed,0xbeffbe44,0xbec63e44,0x3ea23eed,0x3e713efb,0x3ee2bdc8,0x3e15bed5,0xbef5be8e,
0x3e443f00,0x3eed0000,0xbe44bf00,0xbeed0000,0xbeedbeb5,0xbe443eb5,0x3eed3eb5,0x3e44beb5,0x3eed0000,0xbe44bf00,0xbeed0000,0x3e443f00,0xbe443eb5,0x3eed3eb5,0x3e44beb5,0xbeedbeb5,
0xbee20000,0x3e713f00,0x3e15beb5,0xbef5beb5,0x3d49bed5,0xbeffbe8e,0x3ea23efb,0x3ec6bdc8,0x3ec63eed,0x3ea2be44,0xbeffbe44,0x3d493eed,0xbef5bdc8,0x3e153efb,0x3e71be8e,0xbee2bed5,
0xbe8ebf00,0xbed50000,0x3ed50000,0xbe8ebf00,0x3efb3e44,0xbdc8beed,0x3dc83eed,0x3efb3e44,0xbdc83eb5,0x3efb3eb5,0xbefbbeb5,0xbdc83eb5,0xbed5beed,0xbe8e3e44,0x3e8ebe44,0xbed5beed,
0x3ec60000,0xbea2bf00,0x3eff3eb5,0x3d49beb5,0x3e713efb,0x3ee23dc8,0xbe153e8e,0x3ef53ed5,0xbef5be44,0x3e153eed,0xbee2beed,0xbe713e44,0xbd49bed5,0xbeffbe8e,0x3ea2bdc8,0xbec6befb,
0x3f800000,0x0,0x3f800000,0x0,0x3f800000,0x0,0x3f800000,0x0,0x3f800000,0x0,0x3f800000,0x0,0x3f800000,0x0,0x3f800000,0x0,
0x3f800000,0x0,0x3f7fec43,0xbcc90ab0,0x3f7fb10f,0xbd48fb30,0x3f7f4e6d,0xbd96a905,0x3f7ec46d,0xbdc8bd36,0x3f7e1324,0xbdfab273,0x3f7d3aac,0xbe164083,0x3f7c3b28,0xbe2f10a2,
0x3f800000,0x0,0x3f7ffec4,0xbbc90f88,0x3f7ffb11,0xbc490e90,0x3f7ff4e6,0xbc96c9b6,0x3f7fec43,0xbcc90ab0,0x3f7fe129,0xbcfb49ba,0x3f7fd397,0xbd16c32c,0x3f7fc38f,0xbd2fe007,
0x3f800000,0x0,0x3f7fe129,0xbcfb49ba,0x3f7f84ab,0xbd7b2b74,0x3f7eea9d,0xbdbc3ac3,0x3f7e1324,0xbdfab273,0x3f7cfe73,0xbe1c76de,0x3f7baccd,0xbe3b6ecf,0x3f7a1e84,0xbe5a3997,
0x3f800000,0x0,0x3f7ffb11,0xbc490e90,0x3f7fec43,0xbcc90ab0,0x3f7fd397,0xbd16c32c,0x3f7fb10f,0xbd48fb30,0x3f7f84ab,0xbd7b2b74,0x3f7f4e6d,0xbd96a905,0x3f7f0e58,0xbdafb680,
0x3f800000,0x0,0x3f7fd397,0xbd16c32c,0x3f7f4e6d,0xbd96a905,0x3f7e70b0,0xbde1bc2e,0x3f7d3aac,0xbe164083,0x3f7baccd,0xbe3b6ecf,0x3f79c79d,0xbe605c13,0x3f778bc5,0xbe827dc0,
0x3f800000,0x0,0x3f7ff4e6,0xbc96c9b6,0x3f7fd397,0xbd16c32c,0x3f7f9c18,0xbd621469,0x3f7f4e6d,0xbd96a905,0x3f7eea9d,0xbdbc3ac3,0x3f7e70b0,0xbde1bc2e,0x3f7de0b1,0xbe039502,
0x3f800000,0x0,0x3f7fc38f,0xbd2fe007,0x3f7f0e58,0xbdafb680,0x3f7de0b1,0xbe039502,0x3f7c3b28,0xbe2f10a2,0x3f7a1e84,0xbe5a3997,0x3f778bc5,0xbe827dc0,0x3f748422,0xbe97a117,
0x3f800000,0x0,0x3f7fb10f,0xbd48fb30,0x3f7ec46d,0xbdc8bd36,0x3f7d3aac,0xbe164083,0x3f7b14be,0xbe47c5c2,0x3f7853f8,0xbe78cfcc,0x3f74fa0b,0xbe94a031,0x3f710908,0xbeac7cd4,
0x3f800000,0x0,0x3f7f4e6d,0xbd96a905,0x3f7d3aac,0xbe164083,0x3f79c79d,0xbe605c13,0x3f74fa0b,0xbe94a031,0x3f6ed89e,0xbeb8442a,0x3f676bd8,0xbedae880,0x3f5ebe05,0xbefc5d27,
0x3f800000,0x0,0x3f7f9c18,0xbd621469,0x3f7e70b0,0xbde1bc2e,0x3f7c7eb0,0xbe28defc,0x3f79c79d,0xbe605c13,0x3f764d97,0xbe8b9507,0x3f721352,0xbea68f12,0x3f6d1c1d,0xbec1071e,
0x3f800000,0x0,0x3f7f2f9d,0xbda3308c,0x3f7cbfc9,0xbe22abb6,0x3f78b47b,0xbe72b651,0x3f731447,0xbea09ae5,0x3f6be858,0xbec6d529,0x3f633c5a,0xbeebcbbb,0x3f591e6a,0xbf07a136,
0x3f800000,0x0,0x3f7f84ab,0xbd7b2b74,0x3f7e1324,0xbdfab273,0x3f7baccd,0xbe3b6ecf,0x3f7853f8,0xbe78cfcc,0x3f740bdd,0xbe9aa086,0x3f6ed89e,0xbeb8442a,0x3f68bf3c,0xbed53641,
0x3f800000,0x0,0x3f7f0e58,0xbdafb680,0x3f7c3b28,0xbe2f10a2,0x3f778bc5,0xbe827dc0,0x3f710908,0xbeac7cd4,0x3f68bf3c,0xbed53641,0x3f5ebe05,0xbefc5d27,0x3f531849,0xbf10d3cd,
0x3f800000,0x0,0x3f7f6ac7,0xbd8a200a,0x3f7dabcc,0xbe09cf86,0x3f7ac516,0xbe4dee60,0x3f76ba07,0xbe888e93,0x3f718f57,0xbea986c4,0x3f6b4b0c,0xbec9b953,0x3f63f473,0xbee900b7,
0x3f800000,0x0,0x3f7eea9d,0xbdbc3ac3,0x3f7baccd,0xbe3b6ecf,0x3f764d97,0xbe8b9507,0x3f6ed89e,0xbeb8442a,0x3f655e0b,0xbee363fa,0x3f59f26a,0xbf064b82,0x3f4cae79,0xbf19c200,
0x3f800000,0x0,0x3f7ec46d,0xbdc8bd36,0x3f7b14be,0xbe47c5c2,0x3f74fa0b,0xbe94a031,0x3f6c835e,0xbec3ef15,0x3f61c598,0xbef15aea,0x3f54db31,0xbf0e39da,0x3f45e403,0xbf226799,
0x3f800000,0x0,0x3f7e1324,0xbdfab273,0x3f7853f8,0xbe78cfcc,0x3f6ed89e,0xbeb8442a,0x3f61c598,0xbef15aea,0x3f514d3d,0xbf13682a,0x3f3daef9,0xbf2beb4a,0x3f273656,0xbf41d870,
0x3f800000,0x0,0x3f7e9bc9,0xbdd53db9,0x3f7a7302,0xbe541501,0x3f73913f,0xbe9d9e78,0x3f6a09a7,0xbecf7bca,0x3f5df6be,0xbeff17b2,0x3f4f7a1f,0xbf15f6d9,0x3f3ebc1b,0xbf2ac082,
0x3f800000,0x0,0x3f7de0b1,0xbe039502,0x3f778bc5,0xbe827dc0,0x3f6d1c1d,0xbec1071e,0x3f5ebe05,0xbefc5d27,0x3f4cae79,0xbf19c200,0x3f373a23,0xbf32c8c9,0x3f1ebc12,0xbf48d8b3,
0x3f800000,0x0,0x3f7e70b0,0xbde1bc2e,0x3f79c79d,0xbe605c13,0x3f721352,0xbea68f12,0x3f676bd8,0xbedae880,0x3f59f26a,0xbf064b82,0x3f49d112,0xbf1d7fd1,0x3f373a23,0xbf32c8c9,
0x3f800000,0x0,0x3f7dabcc,0xbe09cf86,0x3f76ba07,0xbe888e93,0x3f6b4b0c,0xbec9b953,0x3f5b941a,0xbf039c3d,0x3f47de65,0xbf1ff6cb,0x3f3085bb,0xbf396842,0x3f15f6d9,0xbf4f7a1f,
0x3f800000,0x0,0x3f7e4323,0xbdee3876,0x3f791298,0xbe6c9a7f,0x3f708066,0xbeaf713a,0x3f64aa59,0xbee63375,0x3f55b993,0xbf0cead0,0x3f43e200,0xbf24d225,0x3f2f61a5,0xbf3a7ca4,
0x3f800000,0x0,0x3f7d7474,0xbe1008b7,0x3f75dec6,0xbe8e9a22,0x3f696591,0xbed25a09,0x3f584853,0xbf08f59b,0x3f42de29,0xbf26050a,0x3f299415,0xbf3fc767,0x3f0cead0,0xbf55b993,
0x3f800000,0x0,0x3f7d3aac,0xbe164083,0x3f74fa0b,0xbe94a031,0x3f676bd8,0xbedae880,0x3f54db31,0xbf0e39da,0x3f3daef9,0xbf2beb4a,0x3f226799,0xbf45e403,0x3f039c3d,0xbf5b941a,
0x3f800000,0x0,0x3f7c3b28,0xbe2f10a2,0x3f710908,0xbeac7cd4,0x3f5ebe05,0xbefc5d27,0x3f45e403,0xbf226799,0x3f273656,0xbf41d870,0x3f039c3d,0xbf5b941a,0x3eb8442a,0xbf6ed89e,
0x3f800000,0x0,0x3f7cfe73,0xbe1c76de,0x3f740bdd,0xbe9aa086,0x3f655e0b,0xbee363fa,0x3f514d3d,0xbf13682a,0x3f385216,0xbf31a81d,0x3f1b02c6,0xbf4bbbf8,0x3ef41f07,0xbf6106f2,
0x3f800000,0x0,0x3f7bf531,0xbe354098,0x3f6ff573,0xbeb263ef,0x3f5c61c7,0xbf0242b1,0x3f41d870,0xbf273656,0x3f212ff9,0xbf46e22a,0x3ef6e0cb,0xbf604621,0x3ea395c5,0xbf7294f8,
0x3f800000,0x0,0x3f7cbfc9,0xbe22abb6,0x3f731447,0xbea09ae5,0x3f633c5a,0xbeebcbbb,0x3f4d9f02,0xbf187fc0,0x3f32c8c9,0xbf373a23,0x3f13682a,0xbf514d3d,0x3ee0924f,0xbf660f88,
0x3f800000,0x0,0x3f7baccd,0xbe3b6ecf,0x3f6ed89e,0xbeb8442a,0x3f59f26a,0xbf064b82,0x3f3daef9,0xbf2beb4a,0x3f1b02c6,0xbf4bbbf8,0x3ee63375,0xbf64aa59,0x3e8e9a22,0xbf75dec6,
0x3f800000,0x0,0x3f7c7eb0,0xbe28defc,0x3f721352,0xbea68f12,0x3f6106f2,0xbef41f07,0x3f49d112,0xbf1d7fd1,0x3f2d1469,0xbf3ca003,0x3f0b9a6b,0xbf5695e5,0x3ecc9b8b,0xbf6aab7b,
0x3f800000,0x0,0x3f7b61fc,0xbe419b37,0x3f6db293,0xbebe1d4a,0x3f577026,0xbf0a48ad,0x3f396842,0xbf3085bb,0x3f14b039,0xbf5064af,0x3ed53641,0xbf68bf3c,0x3e72b651,0xbf78b47b,
0x3f800000,0x0,0x3f800000,0x0,0x3f800000,0x0,0x3f800000,0x0,0x3f800000,0x0,0x3f800000,0x0,0x3f800000,0x0,0x3f800000,0x0,
0x3f7b14be,0xbe47c5c2,0x3f79c79d,0xbe605c13,0x3f7853f8,0xbe78cfcc,0x3f76ba07,0xbe888e93,0x3f74fa0b,0xbe94a031,0x3f731447,0xbea09ae5,0x3f710908,0xbeac7cd4,0x3f6ed89e,0xbeb8442a,
0x3f7fb10f,0xbd48fb30,0x3f7f9c18,0xbd621469,0x3f7f84ab,0xbd7b2b74,0x3f7f6ac7,0xbd8a200a,0x3f7f4e6d,0xbd96a905,0x3f7f2f9d,0xbda3308c,0x3f7f0e58,0xbdafb680,0x3f7eea9d,0xbdbc3ac3,
0x3f7853f8,0xbe78cfcc,0x3f764d97,0xbe8b9507,0x3f740bdd,0xbe9aa086,0x3f718f57,0xbea986c4,0x3f6ed89e,0xbeb8442a,0x3f6be858,0xbec6d529,0x3f68bf3c,0xbed53641,0x3f655e0b,0xbee363fa,
0x3f7ec46d,0xbdc8bd36,0x3f7e70b0,0xbde1bc2e,0x3f7e1324,0xbdfab273,0x3f7dabcc,0xbe09cf86,0x3f7d3aac,0xbe164083,0x3f7cbfc9,0xbe22abb6,0x3f7c3b28,0xbe2f10a2,0x3f7baccd,0xbe3b6ecf,
0x3f74fa0b,0xbe94a031,0x3f721352,0xbea68f12,0x3f6ed89e,0xbeb8442a,0x3f6b4b0c,0xbec9b953,0x3f676bd8,0xbedae880,0x3f633c5a,0xbeebcbbb,0x3f5ebe05,0xbefc5d27,0x3f59f26a,0xbf064b82,
0x3f7d3aac,0xbe164083,0x3f7c7eb0,0xbe28defc,0x3f7baccd,0xbe3b6ecf,0x3f7ac516,0xbe4dee60,0x3f79c79d,0xbe605c13,0x3f78b47b,0xbe72b651,0x3f778bc5,0xbe827dc0,0x3f764d97,0xbe8b9507,
0x3f710908,0xbeac7cd4,0x3f6d1c1d,0xbec1071e,0x3f68bf3c,0xbed53641,0x3f63f473,0xbee900b7,0x3f5ebe05,0xbefc5d27,0x3f591e6a,0xbf07a136,0x3f531849,0xbf10d3cd,0x3f4cae79,0xbf19c200,
0x3f6c835e,0xbec3ef15,0x3f676bd8,0xbedae880,0x3f61c598,0xbef15aea,0x3f5b941a,0xbf039c3d,0x3f54db31,0xbf0e39da,0x3f4d9f02,0xbf187fc0,0x3f45e403,0xbf226799,0x3f3daef9,0xbf2beb4a,
0x3f54db31,0xbf0e39da,0x3f49d112,0xbf1d7fd1,0x3f3daef9,0xbf2beb4a,0x3f3085bb,0xbf396842,0x3f226799,0xbf45e403,0x3f13682a,0xbf514d3d,0x3f039c3d,0xbf5b941a,0x3ee63375,0xbf64aa59,
0x3f676bd8,0xbedae880,0x3f6106f2,0xbef41f07,0x3f59f26a,0xbf064b82,0x3f5233c6,0xbf121eb0,0x3f49d112,0xbf1d7fd1,0x3f40d0da,0xbf286605,0x3f373a23,0xbf32c8c9,0x3f2d1469,0xbf3ca003,
0x3f4d9f02,0xbf187fc0,0x3f40d0da,0xbf286605,0x3f32c8c9,0xbf373a23,0x3f239da9,0xbf44e3f5,0x3f13682a,0xbf514d3d,0x3f0242b1,0xbf5c61c7,0x3ee0924f,0xbf660f88,0x3ebb31a0,0xbf6e46be,
0x3f61c598,0xbef15aea,0x3f59f26a,0xbf064b82,0x3f514d3d,0xbf13682a,0x3f47de65,0xbf1ff6cb,0x3f3daef9,0xbf2beb4a,0x3f32c8c9,0xbf373a23,0x3f273656,0xbf41d870,0x3f1b02c6,0xbf4bbbf8,
0x3f45e403,0xbf226799,0x3f373a23,0xbf32c8c9,0x3f273656,0xbf41d870,0x3f15f6d9,0xbf4f7a1f,0x3f039c3d,0xbf5b941a,0x3ee0924f,0xbf660f88,0x3eb8442a,0xbf6ed89e,0x3e8e9a22,0xbf75dec6,
0x3f5b941a,0xbf039c3d,0x3f5233c6,0xbf121eb0,0x3f47de65,0xbf1ff6cb,0x3f3ca003,0xbf2d1469,0x3f3085bb,0xbf396842,0x3f239da9,0xbf44e3f5,0x3f15f6d9,0xbf4f7a1f,0x3f07a136,0xbf591e6a,
0x3f3daef9,0xbf2beb4a,0x3f2d1469,0xbf3ca003,0x3f1b02c6,0xbf4bbbf8,0x3f07a136,0xbf591e6a,0x3ee63375,0xbf64aa59,0x3ebb31a0,0xbf6e46be,0x3e8e9a22,0xbf75dec6,0x3e419b37,0xbf7b61fc,
0x3f3504f3,0xbf3504f3,0x3f226799,0xbf45e403,0x3f0e39da,0xbf54db31,0x3ef15aea,0xbf61c598,0x3ec3ef15,0xbf6c835e,0x3e94a031,0xbf74fa0b,0x3e47c5c2,0xbf7b14be,0x3dc8bd36,0xbf7ec46d,
0x3f0e39da,0xbf54db31,0x3ee63375,0xbf64aa59,0x3eac7cd4,0xbf710908,0x3e605c13,0xbf79c79d,0x3dc8bd36,0xbf7ec46d,0xbcc90ab0,0xbf7fec43,0xbe164083,0xbf7d3aac,0xbe888e93,0xbf76ba07,
0x3f2beb4a,0xbf3daef9,0x3f173c07,0xbf4e8d90,0x3f00e7e4,0xbf5d2d53,0x3ed25a09,0xbf696591,0x3ea09ae5,0xbf731447,0x3e5a3997,0xbf7a1e84,0x3de1bc2e,0xbf7e70b0,0x3bc90f88,0xbf7ffec4,
0x3f039c3d,0xbf5b941a,0x3ecc9b8b,0xbf6aab7b,0x3e8e9a22,0xbf75dec6,0x3e1c76de,0xbf7cfe73,0x3cc90ab0,0xbf7fec43,0xbdd53db9,0xbf7e9bc9,0xbe6c9a7f,0xbf791298,0xbeb554ec,0xbf6f6830,
0x3f226799,0xbf45e403,0x3f0b9a6b,0xbf5695e5,0x3ee63375,0xbf64aa59,0x3eb263ef,0xbf6ff573,0x3e78cfcc,0xbf7853f8,0x3e09cf86,0xbf7dabcc,0x3cc90ab0,0xbf7fec43,0xbdafb680,0xbf7f0e58,
0x3ef15aea,0xbf61c598,0x3eb263ef,0xbf6ff573,0x3e605c13,0xbf79c79d,0x3dafb680,0xbf7f0e58,0xbd48fb30,0xbf7fb10f,0xbe3b6ecf,0xbf7baccd,0xbea09ae5,0xbf731447,0xbee0924f,0xbf660f88,
0x3f187fc0,0xbf4d9f02,0x3eff17b2,0xbf5df6be,0x3ec9b953,0xbf6b4b0c,0x3e919ddd,0xbf756d97,0x3e2f10a2,0xbf7c3b28,0x3d621469,0xbf7f9c18,0xbd7b2b74,0xbf7f84ab,0xbe354098,0xbf7bf531,
0x3edae880,0xbf676bd8,0x3e97a117,0xbf748422,0x3e22abb6,0xbf7cbfc9,0x3c96c9b6,0xbf7ff4e6,0xbdfab273,0xbf7e1324,0xbe8586ce,0xbf772417,0xbec9b953,0xbf6b4b0c,0xbf04f484,0xbf5ac450,
0x3ec3ef15,0xbf6c835e,0x3e78cfcc,0xbf7853f8,0x3dc8bd36,0xbf7ec46d,0xbd48fb30,0xbf7fb10f,0xbe47c5c2,0xbf7b14be,0xbeac7cd4,0xbf710908,0xbef15aea,0xbf61c598,0xbf187fc0,0xbf4d9f02,
0x3e47c5c2,0xbf7b14be,0x3cc90ab0,0xbf7fec43,0xbe164083,0xbf7d3aac,0xbea09ae5,0xbf731447,0xbef15aea,0xbf61c598,0xbf1d7fd1,0xbf49d112,0xbf3daef9,0xbf2beb4a,0xbf584853,0xbf08f59b,
0x3eac7cd4,0xbf710908,0x3e419b37,0xbf7b61fc,0x3d16c32c,0xbf7fd397,0xbdee3876,0xbf7e4323,0xbe888e93,0xbf76ba07,0xbed25a09,0xbf696591,0xbf0b9a6b,0xbf5695e5,0xbf2ac082,0xbf3ebc1b,
0x3e164083,0xbf7d3aac,0xbcfb49ba,0xbf7fe129,0xbe541501,0xbf7a7302,0xbec1071e,0xbf6d1c1d,0xbf08f59b,0xbf584853,0xbf2d1469,0xbf3ca003,0xbf4bbbf8,0xbf1b02c6,0xbf63f473,0xbee900b7,
0x3e94a031,0xbf74fa0b,0x3e09cf86,0xbf7dabcc,0xbcc90ab0,0xbf7fec43,0xbe3b6ecf,0xbf7baccd,0xbeac7cd4,0xbf710908,0xbef6e0cb,0xbf604621,0xbf1d7fd1,0xbf49d112,0xbf3b8f3b,0xbf2e3bde,
0x3dc8bd36,0xbf7ec46d,0xbdafb680,0xbf7f0e58,0xbe888e93,0xbf76ba07,0xbee0924f,0xbf660f88,0xbf187fc0,0xbf4d9f02,0xbf3b8f3b,0xbf2e3bde,0xbf584853,0xbf08f59b,0xbf6db293,0xbebe1d4a,
0x3e78cfcc,0xbf7853f8,0x3da3308c,0xbf7f2f9d,0xbdafb680,0xbf7f0e58,0xbe7ee6e1,0xbf77f110,0xbecf7bca,0xbf6a09a7,0xbf0cead0,0xbf55b993,0xbf2e3bde,0xbf3b8f3b,0xbf4ac77f,0xbf1c420c,
0x3d48fb30,0xbf7fb10f,0xbe1008b7,0xbf7d7474,0xbea68f12,0xbf721352,0xbeff17b2,0xbf5df6be,0xbf273656,0xbf41d870,0xbf48d8b3,0xbf1ebc12,0xbf633c5a,0xbeebcbbb,0xbf756d97,0xbe919ddd,
0x3f800000,0x0,0x3f800000,0x0,0x3f800000,0x0,0x3f800000,0x0,0x3f800000,0x0,0x3f800000,0x0,0x3f800000,0x0,0x3f800000,0x0,
0x3f6c835e,0xbec3ef15,0x3f6a09a7,0xbecf7bca,0x3f676bd8,0xbedae880,0x3f64aa59,0xbee63375,0x3f61c598,0xbef15aea,0x3f5ebe05,0xbefc5d27,0x3f5b941a,0xbf039c3d,0x3f584853,0xbf08f59b,
0x3f7ec46d,0xbdc8bd36,0x3f7e9bc9,0xbdd53db9,0x3f7e70b0,0xbde1bc2e,0x3f7e4323,0xbdee3876,0x3f7e1324,0xbdfab273,0x3f7de0b1,0xbe039502,0x3f7dabcc,0xbe09cf86,0x3f7d7474,0xbe1008b7,
0x3f61c598,0xbef15aea,0x3f5df6be,0xbeff17b2,0x3f59f26a,0xbf064b82,0x3f55b993,0xbf0cead0,0x3f514d3d,0xbf13682a,0x3f4cae79,0xbf19c200,0x3f47de65,0xbf1ff6cb,0x3f42de29,0xbf26050a,
0x3f7b14be,0xbe47c5c2,0x3f7a7302,0xbe541501,0x3f79c79d,0xbe605c13,0x3f791298,0xbe6c9a7f,0x3f7853f8,0xbe78cfcc,0x3f778bc5,0xbe827dc0,0x3f76ba07,0xbe888e93,0x3f75dec6,0xbe8e9a22,
0x3f54db31,0xbf0e39da,0x3f4f7a1f,0xbf15f6d9,0x3f49d112,0xbf1d7fd1,0x3f43e200,0xbf24d225,0x3f3daef9,0xbf2beb4a,0x3f373a23,0xbf32c8c9,0x3f3085bb,0xbf396842,0x3f299415,0xbf3fc767,
0x3f74fa0b,0xbe94a031,0x3f73913f,0xbe9d9e78,0x3f721352,0xbea68f12,0x3f708066,0xbeaf713a,0x3f6ed89e,0xbeb8442a,0x3f6d1c1d,0xbec1071e,0x3f6b4b0c,0xbec9b953,0x3f696591,0xbed25a09,
0x3f45e403,0xbf226799,0x3f3ebc1b,0xbf2ac082,0x3f373a23,0xbf32c8c9,0x3f2f61a5,0xbf3a7ca4,0x3f273656,0xbf41d870,0x3f1ebc12,0xbf48d8b3,0x3f15f6d9,0xbf4f7a1f,0x3f0cead0,0xbf55b993,
0x3f3504f3,0xbf3504f3,0x3f2beb4a,0xbf3daef9,0x3f226799,0xbf45e403,0x3f187fc0,0xbf4d9f02,0x3f0e39da,0xbf54db31,0x3f039c3d,0xbf5b941a,0x3ef15aea,0xbf61c598,0x3edae880,0xbf676bd8,
0x3ec3ef15,0xbf6c835e,0x3ea09ae5,0xbf731447,0x3e78cfcc,0xbf7853f8,0x3e2f10a2,0xbf7c3b28,0x3dc8bd36,0xbf7ec46d,0x3cc90ab0,0xbf7fec43,0xbd48fb30,0xbf7fb10f,0xbdfab273,0xbf7e1324,
0x3f226799,0xbf45e403,0x3f173c07,0xbf4e8d90,0x3f0b9a6b,0xbf5695e5,0x3eff17b2,0xbf5df6be,0x3ee63375,0xbf64aa59,0x3ecc9b8b,0xbf6aab7b,0x3eb263ef,0xbf6ff573,0x3e97a117,0xbf748422,
0x3e94a031,0xbf74fa0b,0x3e5a3997,0xbf7a1e84,0x3e09cf86,0xbf7dabcc,0x3d621469,0xbf7f9c18,0xbcc90ab0,0xbf7fec43,0xbdd53db9,0xbf7e9bc9,0xbe3b6ecf,0xbf7baccd,0xbe8586ce,0xbf772417,
0x3f0e39da,0xbf54db31,0x3f00e7e4,0xbf5d2d53,0x3ee63375,0xbf64aa59,0x3ec9b953,0xbf6b4b0c,0x3eac7cd4,0xbf710908,0x3e8e9a22,0xbf75dec6,0x3e605c13,0xbf79c79d,0x3e22abb6,0xbf7cbfc9,
0x3e47c5c2,0xbf7b14be,0x3de1bc2e,0xbf7e70b0,0x3cc90ab0,0xbf7fec43,0xbd7b2b74,0xbf7f84ab,0xbe164083,0xbf7d3aac,0xbe6c9a7f,0xbf791298,0xbea09ae5,0xbf731447,0xbec9b953,0xbf6b4b0c,
0x3ef15aea,0xbf61c598,0x3ed25a09,0xbf696591,0x3eb263ef,0xbf6ff573,0x3e919ddd,0xbf756d97,0x3e605c13,0xbf79c79d,0x3e1c76de,0xbf7cfe73,0x3dafb680,0xbf7f0e58,0x3c96c9b6,0xbf7ff4e6,
0x3dc8bd36,0xbf7ec46d,0x3bc90f88,0xbf7ffec4,0xbdafb680,0xbf7f0e58,0xbe354098,0xbf7bf531,0xbe888e93,0xbf76ba07,0xbeb554ec,0xbf6f6830,0xbee0924f,0xbf660f88,0xbf04f484,0xbf5ac450,
0x0,0xbf800000,0xbdc8bd36,0xbf7ec46d,0xbe47c5c2,0xbf7b14be,0xbe94a031,0xbf74fa0b,0xbec3ef15,0xbf6c835e,0xbef15aea,0xbf61c598,0xbf0e39da,0xbf54db31,0xbf226799,0xbf45e403,
0xbec3ef15,0xbf6c835e,0xbefc5d27,0xbf5ebe05,0xbf187fc0,0xbf4d9f02,0xbf3085bb,0xbf396842,0xbf45e403,0xbf226799,0xbf584853,0xbf08f59b,0xbf676bd8,0xbedae880,0xbf731447,0xbea09ae5,
0xbdc8bd36,0xbf7ec46d,0xbe4dee60,0xbf7ac516,0xbe9aa086,0xbf740bdd,0xbecc9b8b,0xbf6aab7b,0xbefc5d27,0xbf5ebe05,0xbf14b039,0xbf5064af,0xbf299415,0xbf3fc767,0xbf3ca003,0xbf2d1469,
0xbef15aea,0xbf61c598,0xbf14b039,0xbf5064af,0xbf2e3bde,0xbf3b8f3b,0xbf44e3f5,0xbf239da9,0xbf584853,0xbf08f59b,0xbf6816a8,0xbed8106b,0xbf740bdd,0xbe9aa086,0xbf7bf531,0xbe354098,
0xbe47c5c2,0xbf7b14be,0xbe9aa086,0xbf740bdd,0xbecf7bca,0xbf6a09a7,0xbf00e7e4,0xbf5d2d53,0xbf187fc0,0xbf4d9f02,0xbf2e3bde,0xbf3b8f3b,0xbf41d870,0xbf273656,0xbf531849,0xbf10d3cd,
0xbf0e39da,0xbf54db31,0xbf299415,0xbf3fc767,0xbf41d870,0xbf273656,0xbf5695e5,0xbf0b9a6b,0xbf676bd8,0xbedae880,0xbf740bdd,0xbe9aa086,0xbf7c3b28,0xbe2f10a2,0xbf7fd397,0xbd16c32c,
0xbe94a031,0xbf74fa0b,0xbecc9b8b,0xbf6aab7b,0xbf00e7e4,0xbf5d2d53,0xbf19c200,0xbf4cae79,0xbf3085bb,0xbf396842,0xbf44e3f5,0xbf239da9,0xbf5695e5,0xbf0b9a6b,0xbf655e0b,0xbee363fa,
0xbf226799,0xbf45e403,0xbf3ca003,0xbf2d1469,0xbf531849,0xbf10d3cd,0xbf655e0b,0xbee363fa,0xbf731447,0xbea09ae5,0xbf7bf531,0xbe354098,0xbf7fd397,0xbd16c32c,0xbf7e9bc9,0x3dd53db9,
0xbf3504f3,0xbf3504f3,0xbf4d9f02,0xbf187fc0,0xbf61c598,0xbef15aea,0xbf710908,0xbeac7cd4,0xbf7b14be,0xbe47c5c2,0xbf7fb10f,0xbd48fb30,0xbf7ec46d,0x3dc8bd36,0xbf7853f8,0x3e78cfcc,
0xbf6c835e,0xbec3ef15,0xbf79c79d,0xbe605c13,0xbf7fb10f,0xbd48fb30,0xbf7e1324,0x3dfab273,0xbf74fa0b,0x3e94a031,0xbf64aa59,0x3ee63375,0xbf4d9f02,0x3f187fc0,0xbf3085bb,0x3f396842,
0xbf45e403,0xbf226799,0xbf5c61c7,0xbf0242b1,0xbf6db293,0xbebe1d4a,0xbf796e4e,0xbe667c66,0xbf7f4e6d,0xbd96a905,0xbf7f2f9d,0x3da3308c,0xbf791298,0x3e6c9a7f,0xbf6d1c1d,0x3ec1071e,
0xbf74fa0b,0xbe94a031,0xbf7e4323,0xbdee3876,0xbf7f84ab,0x3d7b2b74,0xbf78b47b,0x3e72b651,0xbf6a09a7,0x3ecf7bca,0xbf53fac3,0x3f0f8784,0xbf373a23,0x3f32c8c9,0xbf14b039,0x3f5064af,
0xbf54db31,0xbf0e39da,0xbf68bf3c,0xbed53641,0xbf76ba07,0xbe888e93,0xbf7e70b0,0xbde1bc2e,0xbf7fb10f,0x3d48fb30,0xbf7a7302,0x3e541501,0xbf6ed89e,0x3eb8442a,0xbf5d2d53,0x3f00e7e4,
0xbf7b14be,0xbe47c5c2,0xbf7ffb11,0xbc490e90,0xbf7c3b28,0x3e2f10a2,0xbf6ff573,0x3eb263ef,0xbf5b941a,0x3f039c3d,0xbf3fc767,0x3f299415,0xbf1d7fd1,0x3f49d112,0xbeebcbbb,0x3f633c5a,
0xbf61c598,0xbef15aea,0xbf7294f8,0xbea395c5,0xbf7cbfc9,0xbe22abb6,0xbf7ffec4,0x3bc90f88,0xbf7c3b28,0x3e2f10a2,0xbf718f57,0x3ea986c4,0xbf604621,0x3ef6e0cb,0xbf48d8b3,0x3f1ebc12,
0xbf7ec46d,0xbdc8bd36,0xbf7eea9d,0x3dbc3ac3,0xbf75dec6,0x3e8e9a22,0xbf63f473,0x3ee900b7,0xbf49d112,0x3f1d7fd1,0xbf286605,0x3f40d0da,0xbf00e7e4,0x3f5d2d53,0xbea986c4,0x3f718f57,
0x3f800000,0x0,0x3f800000,0x0,0x3f800000,0x0,0x3f800000,0x0,0x3f800000,0x0,0x3f800000,0x0,0x3f800000,0x0,0x3f800000,0x0,
0x3f54db31,0xbf0e39da,0x3f514d3d,0xbf13682a,0x3f4d9f02,0xbf187fc0,0x3f49d112,0xbf1d7fd1,0x3f45e403,0xbf226799,0x3f41d870,0xbf273656,0x3f3daef9,0xbf2beb4a,0x3f396842,0xbf3085bb,
0x3f7d3aac,0xbe164083,0x3f7cfe73,0xbe1c76de,0x3f7cbfc9,0xbe22abb6,0x3f7c7eb0,0xbe28defc,0x3f7c3b28,0xbe2f10a2,0x3f7bf531,0xbe354098,0x3f7baccd,0xbe3b6ecf,0x3f7b61fc,0xbe419b37,
0x3f3daef9,0xbf2beb4a,0x3f385216,0xbf31a81d,0x3f32c8c9,0xbf373a23,0x3f2d1469,0xbf3ca003,0x3f273656,0xbf41d870,0x3f212ff9,0xbf46e22a,0x3f1b02c6,0xbf4bbbf8,0x3f14b039,0xbf5064af,
0x3f74fa0b,0xbe94a031,0x3f740bdd,0xbe9aa086,0x3f731447,0xbea09ae5,0x3f721352,0xbea68f12,0x3f710908,0xbeac7cd4,0x3f6ff573,0xbeb263ef,0x3f6ed89e,0xbeb8442a,0x3f6db293,0xbebe1d4a,
0x3f226799,0xbf45e403,0x3f1b02c6,0xbf4bbbf8,0x3f13682a,0xbf514d3d,0x3f0b9a6b,0xbf5695e5,0x3f039c3d,0xbf5b941a,0x3ef6e0cb,0xbf604621,0x3ee63375,0xbf64aa59,0x3ed53641,0xbf68bf3c,
0x3f676bd8,0xbedae880,0x3f655e0b,0xbee363fa,0x3f633c5a,0xbeebcbbb,0x3f6106f2,0xbef41f07,0x3f5ebe05,0xbefc5d27,0x3f5c61c7,0xbf0242b1,0x3f59f26a,0xbf064b82,0x3f577026,0xbf0a48ad,
0x3f039c3d,0xbf5b941a,0x3ef41f07,0xbf6106f2,0x3ee0924f,0xbf660f88,0x3ecc9b8b,0xbf6aab7b,0x3eb8442a,0xbf6ed89e,0x3ea395c5,0xbf7294f8,0x3e8e9a22,0xbf75dec6,0x3e72b651,0xbf78b47b,
0x3ec3ef15,0xbf6c835e,0x3eac7cd4,0xbf710908,0x3e94a031,0xbf74fa0b,0x3e78cfcc,0xbf7853f8,0x3e47c5c2,0xbf7b14be,0x3e164083,0xbf7d3aac,0x3dc8bd36,0xbf7ec46d,0x3d48fb30,0xbf7fb10f,
0xbe47c5c2,0xbf7b14be,0xbe888e93,0xbf76ba07,0xbeac7cd4,0xbf710908,0xbecf7bca,0xbf6a09a7,0xbef15aea,0xbf61c598,0xbf08f59b,0xbf584853,0xbf187fc0,0xbf4d9f02,0xbf273656,0xbf41d870,
0x3e78cfcc,0xbf7853f8,0x3e419b37,0xbf7b61fc,0x3e09cf86,0xbf7dabcc,0x3da3308c,0xbf7f2f9d,0x3cc90ab0,0xbf7fec43,0xbcfb49ba,0xbf7fe129,0xbdafb680,0xbf7f0e58,0xbe1008b7,0xbf7d7474,
0xbeac7cd4,0xbf710908,0xbed25a09,0xbf696591,0xbef6e0cb,0xbf604621,0xbf0cead0,0xbf55b993,0xbf1d7fd1,0xbf49d112,0xbf2d1469,0xbf3ca003,0xbf3b8f3b,0xbf2e3bde,0xbf48d8b3,0xbf1ebc12,
0x3dc8bd36,0xbf7ec46d,0x3d16c32c,0xbf7fd397,0xbcc90ab0,0xbf7fec43,0xbdafb680,0xbf7f0e58,0xbe164083,0xbf7d3aac,0xbe541501,0xbf7a7302,0xbe888e93,0xbf76ba07,0xbea68f12,0xbf721352,
0xbef15aea,0xbf61c598,0xbf0b9a6b,0xbf5695e5,0xbf1d7fd1,0xbf49d112,0xbf2e3bde,0xbf3b8f3b,0xbf3daef9,0xbf2beb4a,0xbf4bbbf8,0xbf1b02c6,0xbf584853,0xbf08f59b,0xbf633c5a,0xbeebcbbb,
0xbd48fb30,0xbf7fb10f,0xbdee3876,0xbf7e4323,0xbe3b6ecf,0xbf7baccd,0xbe7ee6e1,0xbf77f110,0xbea09ae5,0xbf731447,0xbec1071e,0xbf6d1c1d,0xbee0924f,0xbf660f88,0xbeff17b2,0xbf5df6be,
0xbf187fc0,0xbf4d9f02,0xbf2ac082,0xbf3ebc1b,0xbf3b8f3b,0xbf2e3bde,0xbf4ac77f,0xbf1c420c,0xbf584853,0xbf08f59b,0xbf63f473,0xbee900b7,0xbf6db293,0xbebe1d4a,0xbf756d97,0xbe919ddd,
0xbf3504f3,0xbf3504f3,0xbf45e403,0xbf226799,0xbf54db31,0xbf0e39da,0xbf61c598,0xbef15aea,0xbf6c835e,0xbec3ef15,0xbf74fa0b,0xbe94a031,0xbf7b14be,0xbe47c5c2,0xbf7ec46d,0xbdc8bd36,
0xbf7b14be,0xbe47c5c2,0xbf7f4e6d,0xbd96a905,0xbf7fb10f,0x3d48fb30,0xbf7c3b28,0x3e2f10a2,0xbf74fa0b,0x3e94a031,0xbf6a09a7,0x3ecf7bca,0xbf5b941a,0x3f039c3d,0xbf49d112,0x3f1d7fd1,
0xbf4d9f02,0xbf187fc0,0xbf5c61c7,0xbf0242b1,0xbf68bf3c,0xbed53641,0xbf7294f8,0xbea395c5,0xbf79c79d,0xbe605c13,0xbf7e4323,0xbdee3876,0xbf7ffb11,0xbc490e90,0xbf7eea9d,0x3dbc3ac3,
0xbf7fb10f,0xbd48fb30,0xbf7f2f9d,0x3da3308c,0xbf7a7302,0x3e541501,0xbf718f57,0x3ea986c4,0xbf64aa59,0x3ee63375,0xbf53fac3,0x3f0f8784,0xbf3fc767,0x3f299415,0xbf286605,0x3f40d0da,
0xbf61c598,0xbef15aea,0xbf6db293,0xbebe1d4a,0xbf76ba07,0xbe888e93,0xbf7cbfc9,0xbe22abb6,0xbf7fb10f,0xbd48fb30,0xbf7f84ab,0x3d7b2b74,0xbf7c3b28,0x3e2f10a2,0xbf75dec6,0x3e8e9a22,
0xbf7ec46d,0x3dc8bd36,0xbf791298,0x3e6c9a7f,0xbf6ed89e,0x3eb8442a,0xbf604621,0x3ef6e0cb,0xbf4d9f02,0x3f187fc0,0xbf373a23,0x3f32c8c9,0xbf1d7fd1,0x3f49d112,0xbf00e7e4,0x3f5d2d53,
0xbf710908,0xbeac7cd4,0xbf796e4e,0xbe667c66,0xbf7e70b0,0xbde1bc2e,0xbf7ffec4,0x3bc90f88,0xbf7e1324,0x3dfab273,0xbf78b47b,0x3e72b651,0xbf6ff573,0x3eb263ef,0xbf63f473,0x3ee900b7,
0xbf7853f8,0x3e78cfcc,0xbf6d1c1d,0x3ec1071e,0xbf5d2d53,0x3f00e7e4,0xbf48d8b3,0x3f1ebc12,0xbf3085bb,0x3f396842,0xbf14b039,0x3f5064af,0xbeebcbbb,0x3f633c5a,0xbea986c4,0x3f718f57,
0xbf6c835e,0x3ec3ef15,0xbf5b941a,0x3f039c3d,0xbf45e403,0x3f226799,0xbf2beb4a,0x3f3daef9,0xbf0e39da,0x3f54db31,0xbedae880,0x3f676bd8,0xbe94a031,0x3f74fa0b,0xbe164083,0x3f7d3aac,
0xbf0e39da,0x3f54db31,0xbecf7bca,0x3f6a09a7,0xbe78cfcc,0x3f7853f8,0xbd96a905,0x3f7f4e6d,0x3dc8bd36,0x3f7ec46d,0x3e888e93,0x3f76ba07,0x3edae880,0x3f676bd8,0x3f13682a,0x3f514d3d,
0xbf5b941a,0x3f039c3d,0xbf44e3f5,0x3f239da9,0xbf299415,0x3f3fc767,0xbf0a48ad,0x3f577026,0xbecf7bca,0x3f6a09a7,0xbe8586ce,0x3f772417,0xbde1bc2e,0x3f7e70b0,0x3d2fe007,0x3f7fc38f,
0xbedae880,0x3f676bd8,0xbe8586ce,0x3f772417,0xbdafb680,0x3f7f0e58,0x3dbc3ac3,0x3f7eea9d,0x3e888e93,0x3f76ba07,0x3eddbe79,0x3f66becc,0x3f15f6d9,0x3f4f7a1f,0x3f385216,0x3f31a81d,
0xbf45e403,0x3f226799,0xbf299415,0x3f3fc767,0xbf08f59b,0x3f584853,0xbec9b953,0x3f6b4b0c,0xbe78cfcc,0x3f7853f8,0xbdafb680,0x3f7f0e58,0x3d96a905,0x3f7f4e6d,0x3e6c9a7f,0x3f791298,
0xbe94a031,0x3f74fa0b,0xbde1bc2e,0x3f7e70b0,0x3d96a905,0x3f7f4e6d,0x3e827dc0,0x3f778bc5,0x3edae880,0x3f676bd8,0x3f15f6d9,0x3f4f7a1f,0x3f396842,0x3f3085bb,0x3f5695e5,0x3f0b9a6b,
0xbf2beb4a,0x3f3daef9,0xbf0a48ad,0x3f577026,0xbec9b953,0x3f6b4b0c,0xbe72b651,0x3f78b47b,0xbd96a905,0x3f7f4e6d,0x3dbc3ac3,0x3f7eea9d,0x3e827dc0,0x3f778bc5,0x3ed25a09,0x3f696591,
0xbe164083,0x3f7d3aac,0x3d2fe007,0x3f7fc38f,0x3e6c9a7f,0x3f791298,0x3ed25a09,0x3f696591,0x3f13682a,0x3f514d3d,0x3f385216,0x3f31a81d,0x3f5695e5,0x3f0b9a6b,0x3f6d1c1d,0x3ec1071e,
0x3e00,0x3e00,0x3e00,0x3e00,0x3e00,0x3e00,0x3e00,0x3e00,0x3e00,0x3e00,0x3e00,0x3e00,0x3e00,0x3e00,0x3e00,0x3e00,
0xbd443ded,0xbcc83dfb,0xbc493dff,0xbd153df5,0xbdb53db5,0xbdd53d8e,0xbdc63da2,0xbde23d71,0xbe000000,0xbdfbbcc8,0xbdffbc49,0xbdf5bd15,0xbdb5bdb5,0xbd8ebdd5,0xbda2bdc6,0xbd71bde2,
0xbdb53db5,0xbd443ded,0xbcc83dfb,0xbd8e3dd5,0xbe000000,0xbdedbd44,0xbdfbbcc8,0xbdd5bd8e,0xbe00,0x3d44bded,0x3cc8bdfb,0x3d8ebdd5,0x3e000000,0x3ded3d44,0x3dfb3cc8,0x3dd53d8e,
0xbded3d44,0xbd8e3dd5,0xbd153df5,0xbdc63da2,0xbdb5bdb5,0xbcc8bdfb,0xbd71bde2,0x3c49bdff,0x3e000000,0x3dd53d8e,0x3df53d15,0x3da23dc6,0xbdb53db5,0xbdfb3cc8,0xbde23d71,0xbdffbc49,
0xbe000000,0xbdb53db5,0xbd443ded,0xbded3d44,0xbe00,0x3db5bdb5,0x3d44bded,0x3dedbd44,0x3e00,0xbdb53db5,0xbd443ded,0xbded3d44,0xbe00,0x3db5bdb5,0x3d44bded,0x3dedbd44,
0xbdedbd44,0xbdd53d8e,0xbd713de2,0xbdff3c49,0x3db5bdb5,0x3dfb3cc8,0x3df5bd15,0x3dc63da2,0xbe000000,0xbd8ebdd5,0xbde2bd71,0xbc49bdff,0x3db53db5,0xbcc83dfb,0x3d153df5,0xbda23dc6,
0xbdb5bdb5,0xbded3d44,0xbd8e3dd5,0xbdfbbcc8,0x3e000000,0x3d443ded,0x3dd53d8e,0xbcc83dfb,0xbe00,0x3dedbd44,0x3d8ebdd5,0x3dfb3cc8,0xbe000000,0xbd44bded,0xbdd5bd8e,0x3cc8bdfb,
0xbd44bded,0xbdfb3cc8,0xbda23dc6,0xbde2bd71,0x3db53db5,0xbd8e3dd5,0x3c493dff,0xbdf53d15,0x3e000000,0x3cc83dfb,0x3dc63da2,0xbd713de2,0x3db5bdb5,0x3dd53d8e,0x3dffbc49,0x3d153df5,
0xbe00,0xbe000000,0xbdb53db5,0xbdb5bdb5,0x3e00,0xbe000000,0xbdb53db5,0xbdb5bdb5,0x3e00,0xbe000000,0xbdb53db5,0xbdb5bdb5,0x3e00,0xbe000000,0xbdb53db5,0xbdb5bdb5,
0x3d44bded,0xbdfbbcc8,0xbdc63da2,0xbd71bde2,0xbdb53db5,0xbd8ebdd5,0xbdffbc49,0x3d15bdf5,0xbe000000,0x3cc8bdfb,0xbda2bdc6,0x3de2bd71,0xbdb5bdb5,0x3dd5bd8e,0x3c49bdff,0x3df53d15,
0x3db5bdb5,0xbdedbd44,0xbdd53d8e,0xbcc8bdfb,0xbe000000,0x3d44bded,0xbd8ebdd5,0x3dfbbcc8,0xbe00,0x3ded3d44,0x3dd5bd8e,0x3cc83dfb,0x3e000000,0xbd443ded,0x3d8e3dd5,0xbdfb3cc8,
0x3dedbd44,0xbdd5bd8e,0xbde23d71,0x3c49bdff,0xbdb5bdb5,0x3dfbbcc8,0x3d15bdf5,0x3da23dc6,0x3e000000,0xbd8e3dd5,0x3d713de2,0xbdffbc49,0xbdb53db5,0xbcc8bdfb,0xbdf5bd15,0x3dc6bda2,
0x3e000000,0xbdb5bdb5,0xbded3d44,0x3d44bded,0xbe00,0x3db53db5,0x3dedbd44,0xbd443ded,0x3e00,0xbdb5bdb5,0xbded3d44,0x3d44bded,0xbe00,0x3db53db5,0x3dedbd44,0xbd443ded,
0x3ded3d44,0xbd8ebdd5,0xbdf53d15,0x3da2bdc6,0x3db5bdb5,0xbcc83dfb,0x3de23d71,0xbdff3c49,0xbe000000,0x3dd5bd8e,0xbd15bdf5,0x3dc63da2,0x3db53db5,0xbdfbbcc8,0xbd713de2,0xbc49bdff,
0x3db53db5,0xbd44bded,0xbdfb3cc8,0x3dd5bd8e,0x3e000000,0xbded3d44,0x3cc83dfb,0xbd8ebdd5,0xbe00,0x3d443ded,0x3dfbbcc8,0xbdd53d8e,0xbe000000,0x3dedbd44,0xbcc8bdfb,0x3d8e3dd5,
0x3d443ded,0xbcc8bdfb,0xbdff3c49,0x3df5bd15,0x3db53db5,0xbdd5bd8e,0xbda23dc6,0x3d71bde2,0x3e000000,0xbdfb3cc8,0x3c493dff,0xbd15bdf5,0x3db5bdb5,0xbd8e3dd5,0x3dc63da2,0xbde2bd71,
0x3e00,0xbe00,0xbe000000,0x3e000000,0x3e00,0xbe00,0xbe000000,0x3e000000,0x3e00,0xbe00,0xbe000000,0x3e000000,0x3e00,0xbe00,0xbe000000,0x3e000000,
0xbd443ded,0x3cc8bdfb,0xbdffbc49,0x3df53d15,0xbdb53db5,0x3dd5bd8e,0xbda2bdc6,0x3d713de2,0xbe000000,0x3dfb3cc8,0x3c49bdff,0xbd153df5,0xbdb5bdb5,0x3d8e3dd5,0x3dc6bda2,0xbde23d71,
0xbdb53db5,0x3d44bded,0xbdfbbcc8,0x3dd53d8e,0xbe000000,0x3ded3d44,0x3cc8bdfb,0xbd8e3dd5,0xbe00,0xbd443ded,0x3dfb3cc8,0xbdd5bd8e,0x3e000000,0xbdedbd44,0xbcc83dfb,0x3d8ebdd5,
0xbded3d44,0x3d8ebdd5,0xbdf5bd15,0x3da23dc6,0xbdb5bdb5,0x3cc83dfb,0x3de2bd71,0xbdffbc49,0x3e000000,0xbdd5bd8e,0xbd153df5,0x3dc6bda2,0xbdb53db5,0x3dfbbcc8,0xbd71bde2,0xbc493dff,
0xbe000000,0x3db5bdb5,0xbdedbd44,0x3d443ded,0xbe00,0xbdb53db5,0x3ded3d44,0xbd44bded,0x3e00,0x3db5bdb5,0xbdedbd44,0x3d443ded,0xbe00,0xbdb53db5,0x3ded3d44,0xbd44bded,
0xbdedbd44,0x3dd5bd8e,0xbde2bd71,0x3c493dff,0x3db5bdb5,0xbdfbbcc8,0x3d153df5,0x3da2bdc6,0xbe000000,0x3d8e3dd5,0x3d71bde2,0xbdff3c49,0x3db53db5,0x3cc8bdfb,0xbdf53d15,0x3dc63da2,
0xbdb5bdb5,0x3dedbd44,0xbdd5bd8e,0xbcc83dfb,0x3e000000,0xbd44bded,0xbd8e3dd5,0x3dfb3cc8,0xbe00,0xbded3d44,0x3dd53d8e,0x3cc8bdfb,0xbe000000,0x3d443ded,0x3d8ebdd5,0xbdfbbcc8,
0xbd44bded,0x3dfbbcc8,0xbdc6bda2,0xbd713de2,0x3db53db5,0x3d8ebdd5,0xbdff3c49,0x3d153df5,0x3e000000,0xbcc8bdfb,0xbda23dc6,0x3de23d71,0x3db5bdb5,0xbdd5bd8e,0x3c493dff,0x3df5bd15,
0xbe00,0x3e000000,0xbdb5bdb5,0xbdb53db5,0x3e00,0x3e000000,0xbdb5bdb5,0xbdb53db5,0x3e00,0x3e000000,0xbdb5bdb5,0xbdb53db5,0x3e00,0x3e000000,0xbdb5bdb5,0xbdb53db5,
0x3d44bded,0x3dfb3cc8,0xbda2bdc6,0xbde23d71,0xbdb53db5,0x3d8e3dd5,0x3c49bdff,0xbdf5bd15,0xbe000000,0xbcc83dfb,0x3dc6bda2,0xbd71bde2,0xbdb5bdb5,0xbdd53d8e,0x3dff3c49,0x3d15bdf5,
0x3db5bdb5,0x3ded3d44,0xbd8ebdd5,0xbdfb3cc8,0xbe000000,0xbd443ded,0x3dd5bd8e,0xbcc8bdfb,0xbe00,0xbdedbd44,0x3d8e3dd5,0x3dfbbcc8,0x3e000000,0x3d44bded,0xbdd53d8e,0x3cc83dfb,
0x3dedbd44,0x3dd53d8e,0xbd71bde2,0xbdffbc49,0xbdb5bdb5,0xbdfb3cc8,0x3df53d15,0x3dc6bda2,0x3e000000,0x3d8ebdd5,0xbde23d71,0xbc493dff,0xbdb53db5,0x3cc83dfb,0x3d15bdf5,0xbda2bdc6,
0x3e000000,0x3db53db5,0xbd44bded,0xbdedbd44,0xbe00,0xbdb5bdb5,0x3d443ded,0x3ded3d44,0x3e00,0x3db53db5,0xbd44bded,0xbdedbd44,0xbe00,0xbdb5bdb5,0x3d443ded,0x3ded3d44,
0x3ded3d44,0x3d8e3dd5,0xbd15bdf5,0xbdc6bda2,0x3db5bdb5,0x3cc8bdfb,0xbd713de2,0x3c493dff,0xbe000000,0xbdd53d8e,0x3df5bd15,0x3da2bdc6,0x3db53db5,0x3dfb3cc8,0xbde2bd71,0xbdff3c49,
0x3db53db5,0x3d443ded,0xbcc8bdfb,0xbd8ebdd5,0x3e000000,0x3dedbd44,0xbdfb3cc8,0xbdd53d8e,0xbe00,0xbd44bded,0x3cc83dfb,0x3d8e3dd5,0xbe000000,0xbded3d44,0x3dfbbcc8,0x3dd5bd8e,
0x3d443ded,0x3cc83dfb,0xbc49bdff,0xbd15bdf5,0x3db53db5,0x3dd53d8e,0xbdc6bda2,0xbde2bd71,0x3e000000,0x3dfbbcc8,0xbdff3c49,0xbdf53d15,0x3db5bdb5,0x3d8ebdd5,0xbda23dc6,0xbd713de2,
0x3d803d80,0x3e00,0x3e00,0x3e00,0x3e00,0x3e00,0x3e00,0x3e00,0x3e00,0x3e00,0x3e00,0x3e00,0x3e00,0x3e00,0x3e00,0x3e00,
0xbd803d80,0x3cc8bdfb,0x3c49bdff,0x3d15bdf5,0xbded3d44,0x3dd5bd8e,0x3dc6bda2,0x3de2bd71,0xbdedbd44,0x3dfb3cc8,0x3dff3c49,0x3df53d15,0xbd44bded,0x3d8e3dd5,0x3da23dc6,0x3d713de2,
0x3d803d80,0xbd443ded,0xbcc83dfb,0xbd8e3dd5,0xbdb5bdb5,0xbdedbd44,0xbdfbbcc8,0xbdd5bd8e,0x3db5bdb5,0x3d44bded,0x3cc8bdfb,0x3d8ebdd5,0x3db53db5,0x3ded3d44,0x3dfb3cc8,0x3dd53d8e,
0xbd803d80,0x3d8ebdd5,0x3d15bdf5,0x3dc6bda2,0x3d44bded,0x3cc83dfb,0x3d713de2,0xbc493dff,0x3d443ded,0xbdd5bd8e,0xbdf5bd15,0xbda2bdc6,0xbdedbd44,0x3dfbbcc8,0x3de2bd71,0x3dff3c49,
0x3d803d80,0xbdb53db5,0xbd443ded,0xbded3d44,0x3e000000,0x3db5bdb5,0x3d44bded,0x3dedbd44,0xbe000000,0xbdb53db5,0xbd443ded,0xbded3d44,0x3e000000,0x3db5bdb5,0x3d44bded,0x3dedbd44,
0xbd803d80,0x3dd5bd8e,0x3d71bde2,0x3dffbc49,0x3d443ded,0xbdfbbcc8,0xbdf53d15,0xbdc6bda2,0x3d44bded,0x3d8e3dd5,0x3de23d71,0x3c493dff,0xbded3d44,0x3cc8bdfb,0xbd15bdf5,0x3da2bdc6,
0x3d803d80,0xbded3d44,0xbd8e3dd5,0xbdfbbcc8,0xbdb53db5,0x3d443ded,0x3dd53d8e,0xbcc83dfb,0x3db53db5,0x3dedbd44,0x3d8ebdd5,0x3dfb3cc8,0x3db5bdb5,0xbd44bded,0xbdd5bd8e,0x3cc8bdfb,
0xbd803d80,0x3dfbbcc8,0x3da2bdc6,0x3de23d71,0xbdedbd44,0x3d8ebdd5,0xbc49bdff,0x3df5bd15,0xbded3d44,0xbcc8bdfb,0xbdc6bda2,0x3d71bde2,0xbd443ded,0xbdd5bd8e,0xbdff3c49,0xbd15bdf5,
0x3d803d80,0xbe000000,0xbdb53db5,0xbdb5bdb5,0xbe00,0xbe000000,0xbdb53db5,0xbdb5bdb5,0xbe00,0xbe000000,0xbdb53db5,0xbdb5bdb5,0xbe00,0xbe000000,0xbdb53db5,0xbdb5bdb5,
0xbd803d80,0x3dfb3cc8,0x3dc6bda2,0x3d713de2,0x3dedbd44,0x3d8e3dd5,0x3dff3c49,0xbd153df5,0x3ded3d44,0xbcc83dfb,0x3da23dc6,0xbde23d71,0x3d443ded,0xbdd53d8e,0xbc493dff,0xbdf5bd15,
0x3d803d80,0xbdedbd44,0xbdd53d8e,0xbcc8bdfb,0x3db53db5,0x3d44bded,0xbd8ebdd5,0x3dfbbcc8,0xbdb53db5,0x3ded3d44,0x3dd5bd8e,0x3cc83dfb,0xbdb5bdb5,0xbd443ded,0x3d8e3dd5,0xbdfb3cc8,
0xbd803d80,0x3dd53d8e,0x3de2bd71,0xbc493dff,0xbd443ded,0xbdfb3cc8,0xbd153df5,0xbda2bdc6,0xbd44bded,0x3d8ebdd5,0xbd71bde2,0x3dff3c49,0x3ded3d44,0x3cc83dfb,0x3df53d15,0xbdc63da2,
0x3d803d80,0xbdb5bdb5,0xbded3d44,0x3d44bded,0xbe000000,0x3db53db5,0x3dedbd44,0xbd443ded,0x3e000000,0xbdb5bdb5,0xbded3d44,0x3d44bded,0xbe000000,0x3db53db5,0x3dedbd44,0xbd443ded,
0xbd803d80,0x3d8e3dd5,0x3df5bd15,0xbda23dc6,0xbd44bded,0x3cc8bdfb,0xbde2bd71,0x3dffbc49,0xbd443ded,0xbdd53d8e,0x3d153df5,0xbdc6bda2,0x3dedbd44,0x3dfb3cc8,0x3d71bde2,0x3c493dff,
0x3d803d80,0xbd44bded,0xbdfb3cc8,0x3dd5bd8e,0x3db5bdb5,0xbded3d44,0x3cc83dfb,0xbd8ebdd5,0xbdb5bdb5,0x3d443ded,0x3dfbbcc8,0xbdd53d8e,0xbdb53db5,0x3dedbd44,0xbcc8bdfb,0x3d8e3dd5,
0xbd803d80,0x3cc83dfb,0x3dffbc49,0xbdf53d15,0x3ded3d44,0x3dd53d8e,0x3da2bdc6,0xbd713de2,0x3dedbd44,0x3dfbbcc8,0xbc49bdff,0x3d153df5,0x3d44bded,0x3d8ebdd5,0xbdc6bda2,0x3de23d71,
0x3d803d80,0xbe00,0xbe000000,0x3e000000,0x3e00,0xbe00,0xbe000000,0x3e000000,0x3e00,0xbe00,0xbe000000,0x3e000000,0x3e00,0xbe00,0xbe000000,0x3e000000,
0xbd803d80,0xbcc83dfb,0x3dff3c49,0xbdf5bd15,0xbded3d44,0xbdd53d8e,0x3da23dc6,0xbd71bde2,0xbdedbd44,0xbdfbbcc8,0xbc493dff,0x3d15bdf5,0xbd44bded,0xbd8ebdd5,0xbdc63da2,0x3de2bd71,
0x3d803d80,0x3d44bded,0xbdfbbcc8,0x3dd53d8e,0xbdb5bdb5,0x3ded3d44,0x3cc8bdfb,0xbd8e3dd5,0x3db5bdb5,0xbd443ded,0x3dfb3cc8,0xbdd5bd8e,0x3db53db5,0xbdedbd44,0xbcc83dfb,0x3d8ebdd5,
0xbd803d80,0xbd8e3dd5,0x3df53d15,0xbda2bdc6,0x3d44bded,0xbcc8bdfb,0xbde23d71,0x3dff3c49,0x3d443ded,0x3dd53d8e,0x3d15bdf5,0xbdc63da2,0xbdedbd44,0xbdfb3cc8,0x3d713de2,0x3c49bdff,
0x3d803d80,0x3db5bdb5,0xbdedbd44,0x3d443ded,0x3e000000,0xbdb53db5,0x3ded3d44,0xbd44bded,0xbe000000,0x3db5bdb5,0xbdedbd44,0x3d443ded,0x3e000000,0xbdb53db5,0x3ded3d44,0xbd44bded,
0xbd803d80,0xbdd53d8e,0x3de23d71,0xbc49bdff,0x3d443ded,0x3dfb3cc8,0xbd15bdf5,0xbda23dc6,0x3d44bded,0xbd8ebdd5,0xbd713de2,0x3dffbc49,0xbded3d44,0xbcc83dfb,0x3df5bd15,0xbdc6bda2,
0x3d803d80,0x3dedbd44,0xbdd5bd8e,0xbcc83dfb,0xbdb53db5,0xbd44bded,0xbd8e3dd5,0x3dfb3cc8,0x3db53db5,0xbded3d44,0x3dd53d8e,0x3cc8bdfb,0x3db5bdb5,0x3d443ded,0x3d8ebdd5,0xbdfbbcc8,
0xbd803d80,0xbdfb3cc8,0x3dc63da2,0x3d71bde2,0xbdedbd44,0xbd8e3dd5,0x3dffbc49,0xbd15bdf5,0xbded3d44,0x3cc83dfb,0x3da2bdc6,0xbde2bd71,0xbd443ded,0x3dd53d8e,0xbc49bdff,0xbdf53d15,
0x3d803d80,0x3e000000,0xbdb5bdb5,0xbdb53db5,0xbe00,0x3e000000,0xbdb5bdb5,0xbdb53db5,0xbe00,0x3e000000,0xbdb5bdb5,0xbdb53db5,0xbe00,0x3e000000,0xbdb5bdb5,0xbdb53db5,
0xbd803d80,0xbdfbbcc8,0x3da23dc6,0x3de2bd71,0x3dedbd44,0xbd8ebdd5,0xbc493dff,0x3df53d15,0x3ded3d44,0x3cc8bdfb,0xbdc63da2,0x3d713de2,0x3d443ded,0x3dd5bd8e,0xbdffbc49,0xbd153df5,
0x3d803d80,0x3ded3d44,0xbd8ebdd5,0xbdfb3cc8,0x3db53db5,0xbd443ded,0x3dd5bd8e,0xbcc8bdfb,0xbdb53db5,0xbdedbd44,0x3d8e3dd5,0x3dfbbcc8,0xbdb5bdb5,0x3d44bded,0xbdd53d8e,0x3cc83dfb,
0xbd803d80,0xbdd5bd8e,0x3d713de2,0x3dff3c49,0xbd443ded,0x3dfbbcc8,0xbdf5bd15,0xbdc63da2,0xbd44bded,0xbd8e3dd5,0x3de2bd71,0x3c49bdff,0x3ded3d44,0xbcc8bdfb,0xbd153df5,0x3da23dc6,
0x3d803d80,0x3db53db5,0xbd44bded,0xbdedbd44,0xbe000000,0xbdb5bdb5,0x3d443ded,0x3ded3d44,0x3e000000,0x3db53db5,0xbd44bded,0xbdedbd44,0xbe000000,0xbdb5bdb5,0x3d443ded,0x3ded3d44,
0xbd803d80,0xbd8ebdd5,0x3d153df5,0x3dc63da2,0xbd44bded,0xbcc83dfb,0x3d71bde2,0xbc49bdff,0xbd443ded,0x3dd5bd8e,0xbdf53d15,0xbda23dc6,0x3dedbd44,0xbdfbbcc8,0x3de23d71,0x3dffbc49,
0x3d803d80,0x3d443ded,0xbcc8bdfb,0xbd8ebdd5,0x3db5bdb5,0x3dedbd44,0xbdfb3cc8,0xbdd53d8e,0xbdb5bdb5,0xbd44bded,0x3cc83dfb,0x3d8e3dd5,0xbdb53db5,0xbded3d44,0x3dfbbcc8,0x3dd5bd8e,
0xbd803d80,0xbcc8bdfb,0x3c493dff,0x3d153df5,0x3ded3d44,0xbdd5bd8e,0x3dc63da2,0x3de23d71,0x3dedbd44,0xbdfb3cc8,0x3dffbc49,0x3df5bd15,0x3d44bded,0xbd8e3dd5,0x3da2bdc6,0x3d71bde2,
0xbc493dff,0xbbc93e00,0xbb493e00,0xbc173dff,0xbcc83dfb,0xbcf93df8,0xbce03dfa,0xbd093df7,0xbd443ded,0xbd5b3de7,0xbd4f3dea,0xbd663de5,0xbd8e3dd5,0xbd983dce,0xbd933dd1,0xbd9d3dca,
0xbd713de2,0xbcf93df8,0xbc7b3dfe,0xbd383def,0xbdd53d8e,0xbdf13d2c,0xbde53d66,0xbdfa3ce0,0xbdedbd44,0xbdcebd98,0xbddfbd7c,0xbdb9bdb1,0xbcc8bdfb,0x3bc9be00,0xbc17bdff,0x3cafbdfc,
0xbdc63da2,0xbd5b3de7,0xbce03dfa,0xbd9d3dca,0xbdfbbcc8,0xbdcebd98,0xbdeabd4f,0xbda7bdc2,0x3d44bded,0x3dbebdac,0x3d93bdd1,0x3ddfbd7c,0x3dd53d8e,0x3d843ddc,0x3db13db9,0x3d213df3,
0xbdf53d15,0xbd983dce,0xbd213df3,0xbdd13d93,0xbd8ebdd5,0x3bc9be00,0xbd09bdf7,0x3d38bdef,0x3ded3d44,0x3d843ddc,0x3dc23da7,0x3ce03dfa,0xbdfb3cc8,0xbde7bd5b,0xbdfebc7b,0xbdb9bdb1,
0xbdffbc49,0xbdbe3dac,0xbd4f3dea,0xbdf33d21,0x3cc8bdfb,0x3ddcbd84,0x3d93bdd1,0x3dfebc7b,0xbd443ded,0xbdf13d2c,0xbdb93db1,0xbdffbc17,0x3d8ebdd5,0x3dfdbc96,0x3dd8bd89,0x3df73d09,
0xbde2bd71,0xbddc3d84,0xbd7c3ddf,0xbe003b49,0x3dd5bd8e,0x3de73d5b,0x3dffbc17,0x3d933dd1,0xbdedbd44,0xbc96bdfd,0xbd9dbdca,0x3d38bdef,0x3cc83dfb,0xbdbe3dac,0xbd213df3,0xbdfa3ce0,
0xbda2bdc6,0xbdf13d2c,0xbd933dd1,0xbdf7bd09,0x3dfb3cc8,0x3c963dfd,0x3db13db9,0xbd663de5,0x3d44bded,0x3e003bc9,0x3dd8bd89,0x3dca3d9d,0xbdd5bd8e,0x3cf9bdf8,0xbd38bdef,0x3dc2bda7,
0xbd15bdf5,0xbdfd3c96,0xbda73dc2,0xbdd8bd89,0x3d8e3dd5,0xbdbe3dac,0xbc7b3dfe,0xbe003b49,0x3ded3d44,0xbcf93df8,0x3d663de5,0xbdd13d93,0x3dfbbcc8,0x3d2c3df1,0x3ddf3d7c,0xbd383def,
0x3c49bdff,0xbe00bbc9,0xbdb93db1,0xbda7bdc2,0xbcc83dfb,0xbdf8bcf9,0xbdd83d89,0xbd7cbddf,0xbd443ded,0xbde7bd5b,0xbdef3d38,0xbd21bdf3,0xbd8e3dd5,0xbdcebd98,0xbdfc3caf,0xbc7bbdfe,
0x3d71bde2,0xbdf8bcf9,0xbdca3d9d,0xbd4fbdea,0xbdd53d8e,0xbd2cbdf1,0xbdf3bd21,0x3d89bdd8,0xbdedbd44,0x3d98bdce,0xbd09bdf7,0x3e00bb49,0xbcc8bdfb,0x3e003bc9,0x3da7bdc2,0x3d933dd1,
0x3dc6bda2,0xbde7bd5b,0xbdd83d89,0xbc7bbdfe,0xbdfbbcc8,0x3d98bdce,0xbd38bdef,0x3dff3c17,0x3d44bded,0x3dac3dbe,0x3dfcbcaf,0xbd093df7,0x3dd53d8e,0xbddc3d84,0xbb493e00,0xbde5bd66,
0x3df5bd15,0xbdcebd98,0xbde53d66,0x3cafbdfc,0xbd8ebdd5,0x3e003bc9,0x3d7cbddf,0x3d4f3dea,0x3ded3d44,0xbddc3d84,0x3c173dff,0xbdd8bd89,0xbdfb3cc8,0x3d5bbde7,0xbd9dbdca,0x3e00bb49,
0x3dff3c49,0xbdacbdbe,0xbdef3d38,0x3d66bde5,0x3cc8bdfb,0x3d843ddc,0x3dfcbcaf,0xbd9d3dca,0xbd443ded,0xbd2cbdf1,0xbe00bb49,0x3dc2bda7,0x3d8ebdd5,0x3c963dfd,0x3dfa3ce0,0xbddf3d7c,
0x3de23d71,0xbd84bddc,0xbdf73d09,0x3db1bdb9,0x3dd5bd8e,0xbd5b3de7,0x3dc23da7,0xbdfcbcaf,0xbdedbd44,0x3dfdbc96,0x3c7bbdfe,0x3d4f3dea,0x3cc83dfb,0xbdacbdbe,0xbde53d66,0x3d89bdd8,
0x3da23dc6,0xbd2cbdf1,0xbdfc3caf,0x3ddfbd7c,0x3dfb3cc8,0xbdfd3c96,0xbb493e00,0xbd21bdf3,0x3d44bded,0xbbc93e00,0x3dfa3ce0,0xbdfe3c7b,0xbdd5bd8e,0x3df83cf9,0x3d4fbdea,0xbc173dff,
0x3d153df5,0xbc96bdfd,0xbdff3c17,0x3dfabce0,0x3d8e3dd5,0xbdacbdbe,0xbdca3d9d,0x3db1bdb9,0x3ded3d44,0xbdf8bcf9,0xbd213df3,0x3cafbdfc,0x3dfbbcc8,0xbdf13d2c,0x3d093df7,0xbd4fbdea,
0xbc493dff,0x3bc9be00,0xbe00bb49,0x3dff3c17,0xbcc83dfb,0x3cf9bdf8,0xbdfabce0,0x3df73d09,0xbd443ded,0x3d5bbde7,0xbdeabd4f,0x3de53d66,0xbd8e3dd5,0x3d98bdce,0xbdd1bd93,0x3dca3d9d,
0xbd713de2,0x3cf9bdf8,0xbdfebc7b,0x3def3d38,0xbdd53d8e,0x3df1bd2c,0xbd66bde5,0x3ce03dfa,0xbdedbd44,0x3dce3d98,0x3d7cbddf,0xbdb13db9,0xbcc8bdfb,0xbbc93e00,0x3dffbc17,0xbdfcbcaf,
0xbdc63da2,0x3d5bbde7,0xbdfabce0,0x3dca3d9d,0xbdfbbcc8,0x3dce3d98,0x3d4fbdea,0xbdc23da7,0x3d44bded,0xbdbe3dac,0x3dd13d93,0xbd7cbddf,0x3dd53d8e,0xbd84bddc,0xbdb93db1,0x3df3bd21,
0xbdf53d15,0x3d98bdce,0xbdf3bd21,0x3d933dd1,0xbd8ebdd5,0xbbc93e00,0x3df7bd09,0xbdefbd38,0x3ded3d44,0xbd84bddc,0xbda73dc2,0x3dfabce0,0xbdfb3cc8,0x3de73d5b,0x3c7bbdfe,0xbdb13db9,
0xbdffbc49,0x3dbebdac,0xbdeabd4f,0x3d213df3,0x3cc8bdfb,0xbddc3d84,0x3dd13d93,0xbc7bbdfe,0xbd443ded,0x3df1bd2c,0xbdb1bdb9,0xbc173dff,0x3d8ebdd5,0xbdfd3c96,0x3d893dd8,0x3d09bdf7,
0xbde2bd71,0x3ddcbd84,0xbddfbd7c,0x3b493e00,0x3dd5bd8e,0xbde7bd5b,0x3c173dff,0x3dd1bd93,0xbdedbd44,0x3c963dfd,0x3dcabd9d,0xbdefbd38,0x3cc83dfb,0x3dbebdac,0xbdf3bd21,0x3ce03dfa,
0xbda2bdc6,0x3df1bd2c,0xbdd1bd93,0xbd093df7,0x3dfb3cc8,0xbc96bdfd,0xbdb93db1,0x3de53d66,0x3d44bded,0xbe00bbc9,0x3d893dd8,0x3d9dbdca,0xbdd5bd8e,0xbcf93df8,0x3defbd38,0xbda7bdc2,
0xbd15bdf5,0x3dfdbc96,0xbdc2bda7,0xbd893dd8,0x3d8e3dd5,0x3dbebdac,0xbdfebc7b,0x3b493e00,0x3ded3d44,0x3cf9bdf8,0xbde53d66,0x3d933dd1,0x3dfbbcc8,0xbd2cbdf1,0xbd7c3ddf,0x3def3d38,
0x3c49bdff,0x3e003bc9,0xbdb1bdb9,0xbdc23da7,0xbcc83dfb,0x3df83cf9,0xbd89bdd8,0xbddf3d7c,0xbd443ded,0x3de73d5b,0xbd38bdef,0xbdf33d21,0xbd8e3dd5,0x3dce3d98,0xbcafbdfc,0xbdfe3c7b,
0x3d71bde2,0x3df83cf9,0xbd9dbdca,0xbdea3d4f,0xbdd53d8e,0x3d2c3df1,0x3d21bdf3,0xbdd8bd89,0xbdedbd44,0xbd983dce,0x3df7bd09,0xbb49be00,0xbcc8bdfb,0xbe00bbc9,0x3dc23da7,0x3dd1bd93,
0x3dc6bda2,0x3de73d5b,0xbd89bdd8,0xbdfe3c7b,0xbdfbbcc8,0xbd983dce,0x3defbd38,0x3c17bdff,0x3d44bded,0xbdacbdbe,0x3caf3dfc,0x3df73d09,0x3dd53d8e,0x3ddcbd84,0xbe00bb49,0xbd663de5,
0x3df5bd15,0x3dce3d98,0xbd66bde5,0xbdfcbcaf,0xbd8ebdd5,0xbe00bbc9,0x3ddf3d7c,0x3deabd4f,0x3ded3d44,0x3ddcbd84,0xbdff3c17,0xbd893dd8,0xbdfb3cc8,0xbd5b3de7,0x3dcabd9d,0xbb49be00,
0x3dff3c49,0x3dac3dbe,0xbd38bdef,0xbde5bd66,0x3cc8bdfb,0xbd84bddc,0x3caf3dfc,0x3dca3d9d,0xbd443ded,0x3d2c3df1,0x3b49be00,0xbda7bdc2,0x3d8ebdd5,0xbc96bdfd,0xbce03dfa,0x3d7c3ddf,
0x3de23d71,0x3d843ddc,0xbd09bdf7,0xbdb9bdb1,0x3dd5bd8e,0x3d5bbde7,0xbda73dc2,0xbcaf3dfc,0xbdedbd44,0xbdfd3c96,0x3dfe3c7b,0x3deabd4f,0x3cc83dfb,0x3dac3dbe,0xbd66bde5,0xbdd8bd89,
0x3da23dc6,0x3d2c3df1,0xbcafbdfc,0xbd7cbddf,0x3dfb3cc8,0x3dfdbc96,0xbe00bb49,0xbdf33d21,0x3d44bded,0x3bc9be00,0xbce03dfa,0x3c7b3dfe,0xbdd5bd8e,0xbdf8bcf9,0x3dea3d4f,0x3dff3c17,
0x3d153df5,0x3c963dfd,0xbc17bdff,0xbce0bdfa,0x3d8e3dd5,0x3dac3dbe,0xbd9dbdca,0xbdb9bdb1,0x3ded3d44,0x3df83cf9,0xbdf3bd21,0xbdfcbcaf,0x3dfbbcc8,0x3df1bd2c,0xbdf73d09,0xbdea3d4f,
0xbdb53d80,0xbdbe3dac,0xbdb93db1,0xbdc23da7,0xbd153df5,0xbddc3d84,0xbdd83d89,0xbddf3d7c,0xbd713de2,0xbdf13d2c,0xbdef3d38,0xbdf33d21,0xbda23dc6,0xbdfd3c96,0xbdfc3caf,0xbdfe3c7b,
0x3db53d80,0x3ddcbd84,0x3dcabd9d,0x3deabd4f,0xbdff3c49,0x3de73d5b,0x3df33d21,0x3dd83d89,0xbda2bdc6,0x3c963dfd,0x3d093df7,0x3b493e00,0x3d15bdf5,0xbdbe3dac,0xbda73dc2,0xbdd13d93,
0xbdb53d80,0xbdf13d2c,0xbdd83d89,0xbdfe3c7b,0xbd71bde2,0xbc96bdfd,0xbd38bdef,0x3c17bdff,0x3df5bd15,0x3e003bc9,0x3dfcbcaf,0x3df73d09,0x3c493dff,0xbcf93df8,0xbb493e00,0xbd663de5,
0x3db53d80,0x3dfdbc96,0x3de5bd66,0x3dfc3caf,0x3da2bdc6,0xbdbe3dac,0xbd7c3ddf,0xbdea3d4f,0xbc493dff,0x3cf9bdf8,0xbc17bdff,0x3d89bdd8,0xbd71bde2,0x3d2c3df1,0x3d9d3dca,0x3b493e00,
0xbdb53d80,0xbe00bbc9,0xbdef3d38,0xbde5bd66,0x3df53d15,0x3df83cf9,0x3dfcbcaf,0x3dca3d9d,0xbde2bd71,0xbde7bd5b,0xbe00bb49,0xbda7bdc2,0x3dc63da2,0x3dce3d98,0x3dfa3ce0,0x3d7c3ddf,
0x3db53d80,0x3df83cf9,0x3df7bd09,0x3db93db1,0x3c493dff,0xbd2cbdf1,0xbdc2bda7,0x3cafbdfc,0x3dc6bda2,0xbd983dce,0xbc7b3dfe,0xbdea3d4f,0xbdf5bd15,0x3e003bc9,0x3de5bd66,0x3dd83d89,
0xbdb53d80,0xbde7bd5b,0xbdfc3caf,0xbd7cbddf,0xbde23d71,0xbd983dce,0xbb493e00,0xbdf33d21,0x3d153df5,0x3dac3dbe,0x3dfa3ce0,0x3c7b3dfe,0x3dffbc49,0x3ddcbd84,0x3d4fbdea,0x3dff3c17,
0x3db53d80,0x3dce3d98,0x3dffbc17,0x3ce03dfa,0xbdc6bda2,0x3e003bc9,0x3dcabd9d,0x3db93db1,0xbdffbc49,0x3ddcbd84,0x3d21bdf3,0x3dfc3caf,0xbde23d71,0x3d5bbde7,0xbd09bdf7,0x3deabd4f,
0xbdb53d80,0xbdacbdbe,0xbe00bb49,0x3c17bdff,0x3d15bdf5,0xbd84bddc,0xbdfabce0,0x3d09bdf7,0x3d71bde2,0xbd2cbdf1,0xbdeabd4f,0x3d66bde5,0x3da2bdc6,0xbc96bdfd,0xbdd1bd93,0x3d9dbdca,
0x3db53d80,0x3d843ddc,0x3dfe3c7b,0xbd383def,0x3dffbc49,0xbd5b3de7,0x3d663de5,0xbdfa3ce0,0x3da23dc6,0xbdfd3c96,0xbd7c3ddf,0xbdb9bdb1,0xbd153df5,0xbdacbdbe,0xbdff3c17,0x3cafbdfc,
0xbdb53d80,0xbd2cbdf1,0xbdfabce0,0x3d9dbdca,0x3d713de2,0x3dfdbc96,0x3d4fbdea,0x3da73dc2,0xbdf53d15,0xbbc93e00,0x3dd13d93,0xbddf3d7c,0xbc49bdff,0xbdf8bcf9,0xbdb93db1,0xbd21bdf3,
0x3db53d80,0x3c963dfd,0x3df33d21,0xbdd13d93,0xbda23dc6,0xbdacbdbe,0xbdf73d09,0x3d38bdef,0x3c49bdff,0x3df83cf9,0x3da7bdc2,0x3ce03dfa,0x3d713de2,0xbdf13d2c,0xbc7b3dfe,0xbdb9bdb1,
0xbdb53d80,0x3bc9be00,0xbdeabd4f,0x3df3bd21,0xbdf5bd15,0xbcf93df8,0x3dd13d93,0xbdfe3c7b,0x3de23d71,0x3d5bbde7,0xbdb1bdb9,0x3dff3c17,0xbdc6bda2,0xbd983dce,0x3d893dd8,0xbdf7bd09,
0x3db53d80,0xbcf93df8,0x3ddf3d7c,0xbe003b49,0xbc49bdff,0x3df1bd2c,0xbc17bdff,0x3d933dd1,0xbdc63da2,0xbdcebd98,0xbdca3d9d,0x3d38bdef,0x3df53d15,0xbbc93e00,0x3df33d21,0xbdfa3ce0,
0xbdb53d80,0x3d5bbde7,0xbdd1bd93,0x3df73d09,0x3de2bd71,0xbdcebd98,0xbdb93db1,0x3d66bde5,0xbd15bdf5,0xbdbe3dac,0x3d893dd8,0xbdcabd9d,0xbdff3c49,0x3d843ddc,0x3defbd38,0xbdc23da7,
0x3db53d80,0xbd983dce,0x3dc23da7,0xbdd8bd89,0x3dc63da2,0xbbc93e00,0x3dfe3c7b,0xbe003b49,0x3dff3c49,0x3d843ddc,0x3de5bd66,0xbdd13d93,0x3de2bd71,0x3de73d5b,0x3d7cbddf,0xbd383def,
0xbdb53d80,0x3dbebdac,0xbdb1bdb9,0x3da73dc2,0xbd153df5,0x3ddcbd84,0xbd89bdd8,0x3d7c3ddf,0xbd713de2,0x3df1bd2c,0xbd38bdef,0x3d213df3,0xbda23dc6,0x3dfdbc96,0xbcafbdfc,0x3c7b3dfe,
0x3db53d80,0xbddc3d84,0x3d9d3dca,0xbd4fbdea,0xbdff3c49,0xbde7bd5b,0xbd213df3,0x3d89bdd8,0xbda2bdc6,0xbc96bdfd,0xbdf73d09,0x3e00bb49,0x3d15bdf5,0x3dbebdac,0xbdc2bda7,0x3d933dd1,
0xbdb53d80,0x3df1bd2c,0xbd89bdd8,0x3c7b3dfe,0xbd71bde2,0x3c963dfd,0x3defbd38,0xbdffbc17,0x3df5bd15,0xbe00bbc9,0x3caf3dfc,0x3d09bdf7,0x3c493dff,0x3cf9bdf8,0xbe00bb49,0x3de53d66,
0x3db53d80,0xbdfd3c96,0x3d663de5,0x3cafbdfc,0x3da2bdc6,0x3dbebdac,0xbddfbd7c,0x3d4f3dea,0xbc493dff,0xbcf93df8,0x3dffbc17,0xbdd8bd89,0xbd71bde2,0xbd2cbdf1,0xbdca3d9d,0x3e00bb49,
0xbdb53d80,0x3e003bc9,0xbd38bdef,0xbd663de5,0x3df53d15,0xbdf8bcf9,0x3caf3dfc,0x3d9dbdca,0xbde2bd71,0x3de73d5b,0x3b49be00,0xbdc23da7,0x3dc63da2,0xbdcebd98,0xbce03dfa,0x3ddfbd7c,
0x3db53d80,0xbdf8bcf9,0x3d093df7,0x3db1bdb9,0x3c493dff,0x3d2c3df1,0x3da7bdc2,0xbdfcbcaf,0x3dc6bda2,0x3d98bdce,0xbdfebc7b,0x3d4f3dea,0xbdf5bd15,0xbe00bbc9,0x3d663de5,0x3d89bdd8,
0xbdb53d80,0x3de73d5b,0xbcafbdfc,0xbddf3d7c,0xbde23d71,0x3d98bdce,0xbe00bb49,0x3d213df3,0x3d153df5,0xbdacbdbe,0xbce03dfa,0x3dfebc7b,0x3dffbc49,0xbddc3d84,0x3dea3d4f,0x3c17bdff,
0x3db53d80,0xbdcebd98,0x3c173dff,0x3dfabce0,0xbdc6bda2,0xbe00bbc9,0x3d9d3dca,0x3db1bdb9,0xbdffbc49,0xbddc3d84,0x3df33d21,0x3cafbdfc,0xbde23d71,0xbd5b3de7,0x3df7bd09,0xbd4fbdea,
0xbdb53d80,0x3dac3dbe,0x3b49be00,0xbdffbc17,0x3d15bdf5,0x3d843ddc,0x3ce0bdfa,0xbdf7bd09,0x3d71bde2,0x3d2c3df1,0x3d4fbdea,0xbde5bd66,0x3da2bdc6,0x3c963dfd,0x3d93bdd1,0xbdcabd9d,
0x3db53d80,0xbd84bddc,0xbc7b3dfe,0x3def3d38,0x3dffbc49,0x3d5bbde7,0xbde53d66,0x3ce03dfa,0x3da23dc6,0x3dfdbc96,0xbddfbd7c,0xbdb13db9,0xbd153df5,0x3dac3dbe,0xbc17bdff,0xbdfcbcaf,
0xbdb53d80,0x3d2c3df1,0x3ce0bdfa,0xbdcabd9d,0x3d713de2,0xbdfd3c96,0x3dea3d4f,0x3dc2bda7,0xbdf53d15,0x3bc9be00,0xbd933dd1,0x3d7c3ddf,0xbc49bdff,0x3df83cf9,0xbdb1bdb9,0xbdf33d21,
0x3db53d80,0xbc96bdfd,0xbd213df3,0x3d933dd1,0xbda23dc6,0x3dac3dbe,0xbd09bdf7,0xbdefbd38,0x3c49bdff,0xbdf8bcf9,0x3dc23da7,0x3dfabce0,0x3d713de2,0x3df1bd2c,0xbdfebc7b,0xbdb13db9,
0xbdb53d80,0xbbc93e00,0x3d4fbdea,0xbd21bdf3,0xbdf5bd15,0x3cf9bdf8,0xbd933dd1,0x3c7b3dfe,0x3de23d71,0xbd5b3de7,0x3db9bdb1,0x3c17bdff,0xbdc6bda2,0x3d98bdce,0xbdd83d89,0xbd093df7,
0x3db53d80,0x3cf9bdf8,0xbd7c3ddf,0x3b493e00,0xbc49bdff,0xbdf13d2c,0x3dffbc17,0x3dd1bd93,0xbdc63da2,0x3dce3d98,0xbd9dbdca,0xbdefbd38,0x3df53d15,0x3bc9be00,0xbd213df3,0x3ce03dfa,
0xbdb53d80,0xbd5b3de7,0x3d93bdd1,0x3d09bdf7,0x3de2bd71,0x3dce3d98,0xbdb1bdb9,0xbde5bd66,0xbd15bdf5,0x3dbebdac,0xbdd83d89,0xbd9d3dca,0xbdff3c49,0xbd84bddc,0x3d383def,0x3da73dc2,
0x3db53d80,0x3d98bdce,0xbda73dc2,0xbd893dd8,0x3dc63da2,0x3bc9be00,0xbc7b3dfe,0x3b493e00,0x3dff3c49,0xbd84bddc,0x3d663de5,0x3d933dd1,0x3de2bd71,0xbde7bd5b,0x3ddf3d7c,0x3def3d38,
0xbcc83dfb,0xbc493dff,0xbbc93e00,0xbc963dfd,0xbd443ded,0xbd713de2,0xbd5b3de7,0xbd843ddc,0xbdb53db5,0xbdc63da2,0xbdbe3dac,0xbdce3d98,0xbded3d44,0xbdf53d15,0xbdf13d2c,0xbdf83cf9,
0xbd8e3dd5,0xbd153df5,0xbc963dfd,0xbd5b3de7,0xbded3d44,0xbdff3c49,0xbdf83cf9,0xbe00bbc9,0xbdb5bdb5,0xbd71bde2,0xbd98bdce,0xbd2cbdf1,0x3d44bded,0x3da2bdc6,0x3d84bddc,0x3dbebdac,
0xbdd53d8e,0xbd713de2,0xbcf93df8,0xbdac3dbe,0xbdedbd44,0xbda2bdc6,0xbdcebd98,0xbd5bbde7,0x3db5bdb5,0x3df5bd15,0x3ddcbd84,0x3e00bbc9,0x3d443ded,0xbc493dff,0x3c963dfd,0xbd2c3df1,
0xbdfb3cc8,0xbda23dc6,0xbd2c3df1,0xbddc3d84,0xbd44bded,0x3d15bdf5,0xbbc9be00,0x3d98bdce,0x3db53db5,0x3c493dff,0x3d5b3de7,0xbcf93df8,0xbdedbd44,0xbd71bde2,0xbdbebdac,0xbc96bdfd,
0xbdfbbcc8,0xbdc63da2,0xbd5b3de7,0xbdf83cf9,0x3d44bded,0x3df5bd15,0x3dbebdac,0x3dfd3c96,0xbdb53db5,0xbdffbc49,0xbdf13d2c,0xbddcbd84,0x3dedbd44,0x3de23d71,0x3e003bc9,0x3d983dce,
0xbdd5bd8e,0xbde23d71,0xbd843ddc,0xbe00bbc9,0x3dedbd44,0x3dc63da2,0x3dfd3c96,0x3d2c3df1,0xbdb5bdb5,0x3d15bdf5,0xbcf9bdf8,0x3dbebdac,0xbd443ded,0xbdff3c49,0xbdce3d98,0xbde7bd5b,
0xbd8ebdd5,0xbdf53d15,0xbd983dce,0xbdf1bd2c,0x3ded3d44,0xbc493dff,0x3d843ddc,0xbdac3dbe,0x3db5bdb5,0x3de23d71,0x3dfdbc96,0x3d5b3de7,0xbd44bded,0x3dc6bda2,0x3cf9bdf8,0x3e00bbc9,
0xbcc8bdfb,0xbdff3c49,0xbdac3dbe,0xbdcebd98,0x3d443ded,0xbde23d71,0xbd2c3df1,0xbdf8bcf9,0x3db53db5,0xbda23dc6,0x3bc93e00,0xbdfd3c96,0x3ded3d44,0xbd153df5,0x3d5b3de7,0xbddc3d84,
0x3cc8bdfb,0xbdffbc49,0xbdbe3dac,0xbd98bdce,0xbd443ded,0xbde2bd71,0xbdf13d2c,0xbcf9bdf8,0xbdb53db5,0xbda2bdc6,0xbe00bbc9,0x3c96bdfd,0xbded3d44,0xbd15bdf5,0xbde7bd5b,0x3d84bddc,
0x3d8ebdd5,0xbdf5bd15,0xbdce3d98,0xbd2cbdf1,0xbded3d44,0xbc49bdff,0xbddcbd84,0x3dbebdac,0xbdb5bdb5,0x3de2bd71,0x3c96bdfd,0x3de73d5b,0x3d44bded,0x3dc63da2,0x3df8bcf9,0xbbc93e00,
0x3dd5bd8e,0xbde2bd71,0xbddc3d84,0xbbc9be00,0xbdedbd44,0x3dc6bda2,0xbc96bdfd,0x3df13d2c,0x3db5bdb5,0x3d153df5,0x3df83cf9,0xbdac3dbe,0x3d443ded,0xbdffbc49,0xbd983dce,0xbd5bbde7,
0x3dfbbcc8,0xbdc6bda2,0xbde73d5b,0x3cf9bdf8,0xbd44bded,0x3df53d15,0x3dacbdbe,0x3c963dfd,0x3db53db5,0xbdff3c49,0xbd2c3df1,0xbd84bddc,0xbdedbd44,0x3de2bd71,0xbbc9be00,0x3dce3d98,
0x3dfb3cc8,0xbda2bdc6,0xbdf13d2c,0x3d84bddc,0x3d44bded,0x3d153df5,0x3e003bc9,0xbdce3d98,0xbdb53db5,0x3c49bdff,0xbde7bd5b,0x3df8bcf9,0x3dedbd44,0xbd713de2,0x3dac3dbe,0xbdfdbc96,
0x3dd53d8e,0xbd71bde2,0xbdf83cf9,0x3dbebdac,0x3dedbd44,0xbda23dc6,0x3d983dce,0xbde7bd5b,0xbdb5bdb5,0x3df53d15,0x3d84bddc,0xbbc93e00,0xbd443ded,0xbc49bdff,0xbdfdbc96,0x3df1bd2c,
0x3d8e3dd5,0xbd15bdf5,0xbdfd3c96,0x3de7bd5b,0x3ded3d44,0xbdffbc49,0xbcf93df8,0xbbc9be00,0x3db5bdb5,0xbd713de2,0x3dce3d98,0xbdf1bd2c,0xbd44bded,0x3da23dc6,0x3ddcbd84,0xbdac3dbe,
0x3cc83dfb,0xbc49bdff,0xbe003bc9,0x3dfdbc96,0x3d443ded,0xbd71bde2,0xbde73d5b,0x3ddcbd84,0x3db53db5,0xbdc6bda2,0xbdac3dbe,0x3d98bdce,0x3ded3d44,0xbdf5bd15,0xbd2c3df1,0x3cf9bdf8,
0xbcc83dfb,0x3c49bdff,0xbe00bbc9,0x3dfd3c96,0xbd443ded,0x3d71bde2,0xbde7bd5b,0x3ddc3d84,0xbdb53db5,0x3dc6bda2,0xbdacbdbe,0x3d983dce,0xbded3d44,0x3df5bd15,0xbd2cbdf1,0x3cf93df8,
0xbd8e3dd5,0x3d15bdf5,0xbdfdbc96,0x3de73d5b,0xbded3d44,0x3dffbc49,0xbcf9bdf8,0xbbc93e00,0xbdb5bdb5,0x3d713de2,0x3dcebd98,0xbdf13d2c,0x3d44bded,0xbda23dc6,0x3ddc3d84,0xbdacbdbe,
0xbdd53d8e,0x3d71bde2,0xbdf8bcf9,0x3dbe3dac,0xbdedbd44,0x3da23dc6,0x3d98bdce,0xbde73d5b,0x3db5bdb5,0xbdf53d15,0x3d843ddc,0xbbc9be00,0x3d443ded,0x3c49bdff,0xbdfd3c96,0x3df13d2c,
0xbdfb3cc8,0x3da2bdc6,0xbdf1bd2c,0x3d843ddc,0xbd44bded,0xbd153df5,0x3e00bbc9,0xbdcebd98,0x3db53db5,0xbc49bdff,0xbde73d5b,0x3df83cf9,0xbdedbd44,0x3d713de2,0x3dacbdbe,0xbdfd3c96,
0xbdfbbcc8,0x3dc6bda2,0xbde7bd5b,0x3cf93df8,0x3d44bded,0xbdf53d15,0x3dac3dbe,0x3c96bdfd,0xbdb53db5,0x3dff3c49,0xbd2cbdf1,0xbd843ddc,0x3dedbd44,0xbde2bd71,0xbbc93e00,0x3dcebd98,
0xbdd5bd8e,0x3de2bd71,0xbddcbd84,0xbbc93e00,0x3dedbd44,0xbdc6bda2,0xbc963dfd,0x3df1bd2c,0xbdb5bdb5,0xbd153df5,0x3df8bcf9,0xbdacbdbe,0xbd443ded,0x3dffbc49,0xbd98bdce,0xbd5b3de7,
0xbd8ebdd5,0x3df5bd15,0xbdcebd98,0xbd2c3df1,0x3ded3d44,0x3c49bdff,0xbddc3d84,0x3dbe3dac,0x3db5bdb5,0xbde2bd71,0x3c963dfd,0x3de7bd5b,0xbd44bded,0xbdc63da2,0x3df83cf9,0xbbc9be00,
0xbcc8bdfb,0x3dffbc49,0xbdbebdac,0xbd983dce,0x3d443ded,0x3de2bd71,0xbdf1bd2c,0xbcf93df8,0x3db53db5,0x3da2bdc6,0xbe003bc9,0x3c963dfd,0x3ded3d44,0x3d15bdf5,0xbde73d5b,0x3d843ddc,
0x3cc8bdfb,0x3dff3c49,0xbdacbdbe,0xbdce3d98,0xbd443ded,0x3de23d71,0xbd2cbdf1,0xbdf83cf9,0xbdb53db5,0x3da23dc6,0x3bc9be00,0xbdfdbc96,0xbded3d44,0x3d153df5,0x3d5bbde7,0xbddcbd84,
0x3d8ebdd5,0x3df53d15,0xbd98bdce,0xbdf13d2c,0xbded3d44,0x3c493dff,0x3d84bddc,0xbdacbdbe,0xbdb5bdb5,0xbde23d71,0x3dfd3c96,0x3d5bbde7,0x3d44bded,0xbdc6bda2,0x3cf93df8,0x3e003bc9,
0x3dd5bd8e,0x3de23d71,0xbd84bddc,0xbe003bc9,0xbdedbd44,0xbdc63da2,0x3dfdbc96,0x3d2cbdf1,0x3db5bdb5,0xbd15bdf5,0xbcf93df8,0x3dbe3dac,0x3d443ded,0x3dff3c49,0xbdcebd98,0xbde73d5b,
0x3dfbbcc8,0x3dc63da2,0xbd5bbde7,0xbdf8bcf9,0xbd44bded,0xbdf5bd15,0x3dbe3dac,0x3dfdbc96,0x3db53db5,0x3dffbc49,0xbdf1bd2c,0xbddc3d84,0xbdedbd44,0xbde23d71,0x3e00bbc9,0x3d98bdce,
0x3dfb3cc8,0x3da23dc6,0xbd2cbdf1,0xbddcbd84,0x3d44bded,0xbd15bdf5,0xbbc93e00,0x3d983dce,0xbdb53db5,0xbc493dff,0x3d5bbde7,0xbcf9bdf8,0x3dedbd44,0x3d71bde2,0xbdbe3dac,0xbc963dfd,
0x3dd53d8e,0x3d713de2,0xbcf9bdf8,0xbdacbdbe,0x3dedbd44,0x3da2bdc6,0xbdce3d98,0xbd5b3de7,0xbdb5bdb5,0xbdf5bd15,0x3ddc3d84,0x3e003bc9,0xbd443ded,0x3c493dff,0x3c96bdfd,0xbd2cbdf1,
0x3d8e3dd5,0x3d153df5,0xbc96bdfd,0xbd5bbde7,0x3ded3d44,0x3dff3c49,0xbdf8bcf9,0xbe003bc9,0x3db5bdb5,0x3d71bde2,0xbd983dce,0xbd2c3df1,0xbd44bded,0xbda2bdc6,0x3d843ddc,0x3dbe3dac,
0x3cc83dfb,0x3c493dff,0xbbc9be00,0xbc96bdfd,0x3d443ded,0x3d713de2,0xbd5bbde7,0xbd84bddc,0x3db53db5,0x3dc63da2,0xbdbebdac,0xbdcebd98,0x3ded3d44,0x3df53d15,0xbdf1bd2c,0xbdf8bcf9,
0xbd803d80,0xbdffbc49,0xbe00bbc9,0xbdfdbc96,0xbd8e3dd5,0xbde2bd71,0xbde7bd5b,0xbddcbd84,0xbdd53d8e,0xbda2bdc6,0xbdacbdbe,0xbd98bdce,0xbdfb3cc8,0xbd15bdf5,0xbd2cbdf1,0xbcf9bdf8,
0x3d803d80,0x3df53d15,0x3dfd3c96,0x3de73d5b,0xbdfbbcc8,0x3c493dff,0x3cf93df8,0xbbc93e00,0xbcc8bdfb,0xbde23d71,0xbdce3d98,0xbdf13d2c,0x3dd5bd8e,0xbdc6bda2,0xbddcbd84,0xbdacbdbe,
0xbd803d80,0xbde2bd71,0xbdf8bcf9,0xbdbebdac,0xbcc8bdfb,0x3dc6bda2,0x3d98bdce,0x3de7bd5b,0x3dfb3cc8,0x3d153df5,0x3d843ddc,0x3bc93e00,0xbd8e3dd5,0xbdffbc49,0xbdfd3c96,0xbdf1bd2c,
0x3d803d80,0x3dc63da2,0x3df13d2c,0x3d843ddc,0x3dd5bd8e,0xbdf5bd15,0xbe003bc9,0xbdcebd98,0xbd8e3dd5,0x3dffbc49,0x3de7bd5b,0x3df83cf9,0x3cc8bdfb,0xbde23d71,0xbdac3dbe,0xbdfd3c96,
0xbd803d80,0xbda2bdc6,0xbde7bd5b,0xbcf9bdf8,0x3dd53d8e,0x3d153df5,0x3dac3dbe,0xbc963dfd,0xbd8ebdd5,0x3c49bdff,0xbd2cbdf1,0x3d84bddc,0x3cc83dfb,0xbd713de2,0xbbc93e00,0xbdce3d98,
0x3d803d80,0x3d713de2,0x3ddc3d84,0xbbc93e00,0xbcc83dfb,0x3da2bdc6,0x3c96bdfd,0x3df1bd2c,0x3dfbbcc8,0xbdf5bd15,0xbdf83cf9,0xbdacbdbe,0xbd8ebdd5,0x3c493dff,0x3d983dce,0xbd5b3de7,
0xbd803d80,0xbd15bdf5,0xbdcebd98,0x3d2cbdf1,0xbdfb3cc8,0xbdffbc49,0xbddc3d84,0xbdbebdac,0xbcc83dfb,0xbd713de2,0x3c963dfd,0xbde73d5b,0x3dd53d8e,0x3da23dc6,0x3df83cf9,0x3bc93e00,
0x3d803d80,0x3c493dff,0x3dbe3dac,0xbd983dce,0xbd8ebdd5,0x3d713de2,0x3df13d2c,0xbcf93df8,0xbdd5bd8e,0x3dc63da2,0x3e00bbc9,0x3c963dfd,0xbdfbbcc8,0x3df53d15,0x3de7bd5b,0x3d843ddc,
0xbd803d80,0x3c49bdff,0xbdacbdbe,0x3dcebd98,0x3d8ebdd5,0x3d71bde2,0xbd2cbdf1,0x3df8bcf9,0x3dd5bd8e,0x3dc6bda2,0x3bc9be00,0x3dfd3c96,0x3dfbbcc8,0x3df5bd15,0x3d5bbde7,0x3ddc3d84,
0x3d803d80,0xbd153df5,0x3d983dce,0xbdf13d2c,0x3dfb3cc8,0xbdff3c49,0xbd843ddc,0xbdacbdbe,0x3cc83dfb,0xbd71bde2,0xbdfdbc96,0x3d5bbde7,0xbdd53d8e,0x3da2bdc6,0xbcf9bdf8,0x3e003bc9,
0xbd803d80,0x3d71bde2,0xbd84bddc,0x3e00bbc9,0x3cc83dfb,0x3da23dc6,0x3dfdbc96,0xbd2c3df1,0xbdfbbcc8,0xbdf53d15,0xbcf93df8,0xbdbebdac,0x3d8ebdd5,0x3c49bdff,0xbdcebd98,0x3de7bd5b,
0x3d803d80,0xbda23dc6,0x3d5b3de7,0xbdf8bcf9,0xbdd53d8e,0x3d15bdf5,0xbdbebdac,0x3dfdbc96,0x3d8ebdd5,0x3c493dff,0x3df13d2c,0xbddc3d84,0xbcc83dfb,0xbd71bde2,0xbe003bc9,0x3d98bdce,
0xbd803d80,0x3dc6bda2,0xbd2cbdf1,0x3ddc3d84,0xbdd5bd8e,0xbdf53d15,0xbbc93e00,0xbd98bdce,0x3d8e3dd5,0x3dff3c49,0x3d5bbde7,0x3cf93df8,0xbcc8bdfb,0xbde2bd71,0xbdbe3dac,0x3c96bdfd,
0x3d803d80,0xbde23d71,0x3cf93df8,0xbdacbdbe,0x3cc8bdfb,0x3dc63da2,0x3dcebd98,0xbd5b3de7,0xbdfb3cc8,0x3d15bdf5,0xbddcbd84,0x3e003bc9,0x3d8e3dd5,0xbdff3c49,0xbc963dfd,0xbd2cbdf1,
0xbd803d80,0x3df5bd15,0xbc96bdfd,0x3d5b3de7,0x3dfbbcc8,0x3c49bdff,0xbdf8bcf9,0x3e00bbc9,0x3cc8bdfb,0xbde2bd71,0xbd983dce,0x3d2cbdf1,0xbdd5bd8e,0xbdc63da2,0x3d843ddc,0xbdbebdac,
0x3d803d80,0xbdff3c49,0x3bc93e00,0xbc96bdfd,0x3d8e3dd5,0xbde23d71,0x3d5b3de7,0xbd84bddc,0x3dd53d8e,0xbda23dc6,0x3dbe3dac,0xbdcebd98,0x3dfb3cc8,0xbd153df5,0x3df13d2c,0xbdf8bcf9,
0xbd803d80,0x3dff3c49,0x3bc9be00,0xbc963dfd,0xbd8e3dd5,0x3de23d71,0x3d5bbde7,0xbd843ddc,0xbdd53d8e,0x3da23dc6,0x3dbebdac,0xbdce3d98,0xbdfb3cc8,0x3d153df5,0x3df1bd2c,0xbdf83cf9,
0x3d803d80,0xbdf5bd15,0xbc963dfd,0x3d5bbde7,0xbdfbbcc8,0xbc49bdff,0xbdf83cf9,0x3e003bc9,0xbcc8bdfb,0x3de2bd71,0xbd98bdce,0x3d2c3df1,0x3dd5bd8e,0x3dc63da2,0x3d84bddc,0xbdbe3dac,
0xbd803d80,0x3de23d71,0x3cf9bdf8,0xbdac3dbe,0xbcc8bdfb,0xbdc63da2,0x3dce3d98,0xbd5bbde7,0x3dfb3cc8,0xbd15bdf5,0xbddc3d84,0x3e00bbc9,0xbd8e3dd5,0x3dff3c49,0xbc96bdfd,0xbd2c3df1,
0x3d803d80,0xbdc6bda2,0xbd2c3df1,0x3ddcbd84,0x3dd5bd8e,0x3df53d15,0xbbc9be00,0xbd983dce,0xbd8e3dd5,0xbdff3c49,0x3d5b3de7,0x3cf9bdf8,0x3cc8bdfb,0x3de2bd71,0xbdbebdac,0x3c963dfd,
0xbd803d80,0x3da23dc6,0x3d5bbde7,0xbdf83cf9,0x3dd53d8e,0xbd15bdf5,0xbdbe3dac,0x3dfd3c96,0xbd8ebdd5,0xbc493dff,0x3df1bd2c,0xbddcbd84,0x3cc83dfb,0x3d71bde2,0xbe00bbc9,0x3d983dce,
0x3d803d80,0xbd71bde2,0xbd843ddc,0x3e003bc9,0xbcc83dfb,0xbda23dc6,0x3dfd3c96,0xbd2cbdf1,0x3dfbbcc8,0x3df53d15,0xbcf9bdf8,0xbdbe3dac,0xbd8ebdd5,0xbc49bdff,0xbdce3d98,0x3de73d5b,
0xbd803d80,0x3d153df5,0x3d98bdce,0xbdf1bd2c,0xbdfb3cc8,0x3dff3c49,0xbd84bddc,0xbdac3dbe,0xbcc83dfb,0x3d71bde2,0xbdfd3c96,0x3d5b3de7,0x3dd53d8e,0xbda2bdc6,0xbcf93df8,0x3e00bbc9,
0x3d803d80,0xbc49bdff,0xbdac3dbe,0x3dce3d98,0xbd8ebdd5,0xbd71bde2,0xbd2c3df1,0x3df83cf9,0xbdd5bd8e,0xbdc6bda2,0x3bc93e00,0x3dfdbc96,0xbdfbbcc8,0xbdf5bd15,0x3d5b3de7,0x3ddcbd84,
0xbd803d80,0xbc493dff,0x3dbebdac,0xbd98bdce,0x3d8ebdd5,0xbd713de2,0x3df1bd2c,0xbcf9bdf8,0x3dd5bd8e,0xbdc63da2,0x3e003bc9,0x3c96bdfd,0x3dfbbcc8,0xbdf53d15,0x3de73d5b,0x3d84bddc,
0x3d803d80,0x3d15bdf5,0xbdce3d98,0x3d2c3df1,0x3dfb3cc8,0x3dffbc49,0xbddcbd84,0xbdbe3dac,0x3cc83dfb,0x3d713de2,0x3c96bdfd,0xbde7bd5b,0xbdd53d8e,0xbda23dc6,0x3df8bcf9,0x3bc9be00,
0xbd803d80,0xbd713de2,0x3ddcbd84,0xbbc9be00,0x3cc83dfb,0xbda2bdc6,0x3c963dfd,0x3df13d2c,0xbdfbbcc8,0x3df5bd15,0xbdf8bcf9,0xbdac3dbe,0x3d8ebdd5,0xbc493dff,0x3d98bdce,0xbd5bbde7,
0x3d803d80,0x3da2bdc6,0xbde73d5b,0xbcf93df8,0xbdd53d8e,0xbd153df5,0x3dacbdbe,0xbc96bdfd,0x3d8ebdd5,0xbc49bdff,0xbd2c3df1,0x3d843ddc,0xbcc83dfb,0x3d713de2,0xbbc9be00,0xbdcebd98,
0xbd803d80,0xbdc63da2,0x3df1bd2c,0x3d84bddc,0xbdd5bd8e,0x3df5bd15,0xbe00bbc9,0xbdce3d98,0x3d8e3dd5,0xbdffbc49,0x3de73d5b,0x3df8bcf9,0xbcc8bdfb,0x3de23d71,0xbdacbdbe,0xbdfdbc96,
0x3d803d80,0x3de2bd71,0xbdf83cf9,0xbdbe3dac,0x3cc8bdfb,0xbdc6bda2,0x3d983dce,0x3de73d5b,0xbdfb3cc8,0xbd153df5,0x3d84bddc,0x3bc9be00,0x3d8e3dd5,0x3dffbc49,0xbdfdbc96,0xbdf13d2c,
0xbd803d80,0xbdf53d15,0x3dfdbc96,0x3de7bd5b,0x3dfbbcc8,0xbc493dff,0x3cf9bdf8,0xbbc9be00,0x3cc8bdfb,0x3de23d71,0xbdcebd98,0xbdf1bd2c,0xbdd5bd8e,0x3dc6bda2,0xbddc3d84,0xbdac3dbe,
0x3d803d80,0x3dffbc49,0xbe003bc9,0xbdfd3c96,0x3d8e3dd5,0x3de2bd71,0xbde73d5b,0xbddc3d84,0x3dd53d8e,0x3da2bdc6,0xbdac3dbe,0xbd983dce,0x3dfb3cc8,0x3d15bdf5,0xbd2c3df1,0xbcf93df8,
0xbd153df5,0xbc963dfd,0xbc173dff,0xbce03dfa,0xbd8e3dd5,0xbdac3dbe,0xbd9d3dca,0xbdb93db1,0xbded3d44,0xbdf83cf9,0xbdf33d21,0xbdfc3caf,0xbdfbbcc8,0xbdf1bd2c,0xbdf7bd09,0xbdeabd4f,
0xbda23dc6,0xbd2c3df1,0xbcaf3dfc,0xbd7c3ddf,0xbdfb3cc8,0xbdfdbc96,0xbe003b49,0xbdf3bd21,0xbd44bded,0xbbc9be00,0xbce0bdfa,0x3c7bbdfe,0x3dd5bd8e,0x3df8bcf9,0x3deabd4f,0x3dffbc17,
0xbde23d71,0xbd843ddc,0xbd093df7,0xbdb93db1,0xbdd5bd8e,0xbd5bbde7,0xbda7bdc2,0xbcafbdfc,0x3dedbd44,0x3dfd3c96,0x3dfebc7b,0x3dea3d4f,0xbcc83dfb,0xbdac3dbe,0xbd663de5,0xbdd83d89,
0xbdff3c49,0xbdac3dbe,0xbd383def,0xbde53d66,0xbcc8bdfb,0x3d84bddc,0x3cafbdfc,0x3dcabd9d,0x3d443ded,0xbd2c3df1,0x3b493e00,0xbda73dc2,0xbd8ebdd5,0x3c96bdfd,0xbce0bdfa,0x3d7cbddf,
0xbdf5bd15,0xbdce3d98,0xbd663de5,0xbdfc3caf,0x3d8ebdd5,0x3e00bbc9,0x3ddfbd7c,0x3dea3d4f,0xbded3d44,0xbddcbd84,0xbdffbc17,0xbd89bdd8,0x3dfb3cc8,0x3d5b3de7,0x3dca3d9d,0xbb493e00,
0xbdc6bda2,0xbde73d5b,0xbd893dd8,0xbdfebc7b,0x3dfbbcc8,0x3d983dce,0x3def3d38,0x3c173dff,0xbd44bded,0x3dacbdbe,0x3cafbdfc,0x3df7bd09,0xbdd53d8e,0xbddcbd84,0xbe003b49,0xbd66bde5,
0xbd71bde2,0xbdf83cf9,0xbd9d3dca,0xbdeabd4f,0x3dd53d8e,0xbd2c3df1,0x3d213df3,0xbdd83d89,0x3dedbd44,0x3d983dce,0x3df73d09,0xbb493e00,0x3cc8bdfb,0x3e00bbc9,0x3dc2bda7,0x3dd13d93,
0xbc49bdff,0xbe003bc9,0xbdb13db9,0xbdc2bda7,0x3cc83dfb,0xbdf83cf9,0xbd893dd8,0xbddfbd7c,0x3d443ded,0xbde73d5b,0xbd383def,0xbdf3bd21,0x3d8e3dd5,0xbdce3d98,0xbcaf3dfc,0xbdfebc7b,
0x3d15bdf5,0xbdfdbc96,0xbdc23da7,0xbd89bdd8,0xbd8e3dd5,0xbdbebdac,0xbdfe3c7b,0x3b49be00,0xbded3d44,0xbcf9bdf8,0xbde5bd66,0x3d93bdd1,0xbdfbbcc8,0x3d2cbdf1,0xbd7cbddf,0x3defbd38,
0x3da2bdc6,0xbdf1bd2c,0xbdd13d93,0xbd09bdf7,0xbdfb3cc8,0x3c96bdfd,0xbdb9bdb1,0x3de5bd66,0xbd44bded,0x3e00bbc9,0x3d89bdd8,0x3d9d3dca,0x3dd5bd8e,0x3cf93df8,0x3def3d38,0xbda73dc2,
0x3de2bd71,0xbddcbd84,0xbddf3d7c,0x3b49be00,0xbdd5bd8e,0x3de7bd5b,0x3c17bdff,0x3dd13d93,0x3dedbd44,0xbc963dfd,0x3dca3d9d,0xbdef3d38,0xbcc83dfb,0xbdbebdac,0xbdf33d21,0x3ce0bdfa,
0x3dffbc49,0xbdbebdac,0xbdea3d4f,0x3d21bdf3,0xbcc8bdfb,0x3ddc3d84,0x3dd1bd93,0xbc7b3dfe,0x3d443ded,0xbdf1bd2c,0xbdb13db9,0xbc17bdff,0xbd8ebdd5,0x3dfd3c96,0x3d89bdd8,0x3d093df7,
0x3df53d15,0xbd98bdce,0xbdf33d21,0x3d93bdd1,0x3d8ebdd5,0x3bc93e00,0x3df73d09,0xbdef3d38,0xbded3d44,0x3d84bddc,0xbda7bdc2,0x3dfa3ce0,0x3dfb3cc8,0xbde73d5b,0x3c7b3dfe,0xbdb1bdb9,
0x3dc63da2,0xbd5bbde7,0xbdfa3ce0,0x3dcabd9d,0x3dfbbcc8,0xbdce3d98,0x3d4f3dea,0xbdc2bda7,0xbd44bded,0x3dbe3dac,0x3dd1bd93,0xbd7c3ddf,0xbdd53d8e,0x3d84bddc,0xbdb9bdb1,0x3df33d21,
0x3d713de2,0xbcf9bdf8,0xbdfe3c7b,0x3defbd38,0x3dd53d8e,0xbdf1bd2c,0xbd663de5,0x3ce0bdfa,0x3dedbd44,0xbdce3d98,0x3d7c3ddf,0xbdb1bdb9,0x3cc8bdfb,0x3bc93e00,0x3dff3c17,0xbdfc3caf,
0x3c493dff,0xbbc9be00,0xbe003b49,0x3dffbc17,0x3cc83dfb,0xbcf9bdf8,0xbdfa3ce0,0x3df7bd09,0x3d443ded,0xbd5bbde7,0xbdea3d4f,0x3de5bd66,0x3d8e3dd5,0xbd98bdce,0xbdd13d93,0x3dcabd9d,
0xbd153df5,0x3c96bdfd,0xbdffbc17,0x3dfa3ce0,0xbd8e3dd5,0x3dacbdbe,0xbdcabd9d,0x3db13db9,0xbded3d44,0x3df8bcf9,0xbd21bdf3,0x3caf3dfc,0xbdfbbcc8,0x3df13d2c,0x3d09bdf7,0xbd4f3dea,
0xbda23dc6,0x3d2cbdf1,0xbdfcbcaf,0x3ddf3d7c,0xbdfb3cc8,0x3dfd3c96,0xbb49be00,0xbd213df3,0xbd44bded,0x3bc93e00,0x3dfabce0,0xbdfebc7b,0x3dd5bd8e,0xbdf83cf9,0x3d4f3dea,0xbc17bdff,
0xbde23d71,0x3d84bddc,0xbdf7bd09,0x3db13db9,0xbdd5bd8e,0x3d5b3de7,0x3dc2bda7,0xbdfc3caf,0x3dedbd44,0xbdfdbc96,0x3c7b3dfe,0x3d4fbdea,0xbcc83dfb,0x3dacbdbe,0xbde5bd66,0x3d893dd8,
0xbdff3c49,0x3dacbdbe,0xbdefbd38,0x3d663de5,0xbcc8bdfb,0xbd843ddc,0x3dfc3caf,0xbd9dbdca,0x3d443ded,0x3d2cbdf1,0xbe003b49,0x3dc23da7,0xbd8ebdd5,0xbc963dfd,0x3dfabce0,0xbddfbd7c,
0xbdf5bd15,0x3dcebd98,0xbde5bd66,0x3caf3dfc,0x3d8ebdd5,0xbe003bc9,0x3d7c3ddf,0x3d4fbdea,0xbded3d44,0x3ddc3d84,0x3c17bdff,0xbdd83d89,0x3dfb3cc8,0xbd5bbde7,0xbd9d3dca,0x3e003b49,
0xbdc6bda2,0x3de7bd5b,0xbdd8bd89,0xbc7b3dfe,0x3dfbbcc8,0xbd98bdce,0xbd383def,0x3dffbc17,0xbd44bded,0xbdac3dbe,0x3dfc3caf,0xbd09bdf7,0xbdd53d8e,0x3ddc3d84,0xbb49be00,0xbde53d66,
0xbd71bde2,0x3df8bcf9,0xbdcabd9d,0xbd4f3dea,0x3dd53d8e,0x3d2cbdf1,0xbdf33d21,0x3d893dd8,0x3dedbd44,0xbd98bdce,0xbd093df7,0x3e003b49,0x3cc8bdfb,0xbe003bc9,0x3da73dc2,0x3d93bdd1,
0xbc49bdff,0x3e00bbc9,0xbdb9bdb1,0xbda73dc2,0x3cc83dfb,0x3df8bcf9,0xbdd8bd89,0xbd7c3ddf,0x3d443ded,0x3de7bd5b,0xbdefbd38,0xbd213df3,0x3d8e3dd5,0x3dcebd98,0xbdfcbcaf,0xbc7b3dfe,
0x3d15bdf5,0x3dfd3c96,0xbda7bdc2,0xbdd83d89,0xbd8e3dd5,0x3dbe3dac,0xbc7bbdfe,0xbe00bb49,0xbded3d44,0x3cf93df8,0x3d66bde5,0xbdd1bd93,0xbdfbbcc8,0xbd2c3df1,0x3ddfbd7c,0xbd38bdef,
0x3da2bdc6,0x3df13d2c,0xbd93bdd1,0xbdf73d09,0xbdfb3cc8,0xbc963dfd,0x3db1bdb9,0xbd66bde5,0xbd44bded,0xbe003bc9,0x3dd83d89,0x3dcabd9d,0x3dd5bd8e,0xbcf9bdf8,0xbd383def,0x3dc23da7,
0x3de2bd71,0x3ddc3d84,0xbd7cbddf,0xbe00bb49,0xbdd5bd8e,0xbde73d5b,0x3dff3c17,0x3d93bdd1,0x3dedbd44,0x3c96bdfd,0xbd9d3dca,0x3d383def,0xbcc83dfb,0x3dbe3dac,0xbd21bdf3,0xbdfabce0,
0x3dffbc49,0x3dbe3dac,0xbd4fbdea,0xbdf3bd21,0xbcc8bdfb,0xbddcbd84,0x3d933dd1,0x3dfe3c7b,0x3d443ded,0x3df13d2c,0xbdb9bdb1,0xbdff3c17,0xbd8ebdd5,0xbdfdbc96,0x3dd83d89,0x3df7bd09,
0x3df53d15,0x3d983dce,0xbd21bdf3,0xbdd1bd93,0x3d8ebdd5,0xbbc9be00,0xbd093df7,0x3d383def,0xbded3d44,0xbd843ddc,0x3dc2bda7,0x3ce0bdfa,0x3dfb3cc8,0x3de7bd5b,0xbdfe3c7b,0xbdb93db1,
0x3dc63da2,0x3d5b3de7,0xbce0bdfa,0xbd9dbdca,0x3dfbbcc8,0x3dcebd98,0xbdea3d4f,0xbda73dc2,0xbd44bded,0xbdbebdac,0x3d933dd1,0x3ddf3d7c,0xbdd53d8e,0xbd843ddc,0x3db1bdb9,0x3d21bdf3,
0x3d713de2,0x3cf93df8,0xbc7bbdfe,0xbd38bdef,0x3dd53d8e,0x3df13d2c,0xbde5bd66,0xbdfabce0,0x3dedbd44,0x3dcebd98,0xbddf3d7c,0xbdb93db1,0x3cc8bdfb,0xbbc9be00,0xbc173dff,0x3caf3dfc,
0x3c493dff,0x3bc93e00,0xbb49be00,0xbc17bdff,0x3cc83dfb,0x3cf93df8,0xbce0bdfa,0xbd09bdf7,0x3d443ded,0x3d5b3de7,0xbd4fbdea,0xbd66bde5,0x3d8e3dd5,0x3d983dce,0xbd93bdd1,0xbd9dbdca,
0xbdb53d80,0xbd98bdce,0xbda7bdc2,0xbd89bdd8,0xbdc63da2,0xbbc9be00,0xbc7bbdfe,0x3b49be00,0xbdff3c49,0x3d84bddc,0x3d66bde5,0x3d93bdd1,0xbde2bd71,0x3de7bd5b,0x3ddfbd7c,0x3defbd38,
0x3db53d80,0x3d5b3de7,0x3d933dd1,0x3d093df7,0xbde2bd71,0xbdce3d98,0xbdb13db9,0xbde53d66,0x3d15bdf5,0xbdbebdac,0xbdd8bd89,0xbd9dbdca,0x3dff3c49,0x3d84bddc,0x3d38bdef,0x3da7bdc2,
0xbdb53d80,0xbcf9bdf8,0xbd7cbddf,0x3b49be00,0x3c49bdff,0x3df13d2c,0x3dff3c17,0x3dd13d93,0x3dc63da2,0xbdce3d98,0xbd9d3dca,0xbdef3d38,0xbdf53d15,0xbbc9be00,0xbd21bdf3,0x3ce0bdfa,
0x3db53d80,0x3bc93e00,0x3d4f3dea,0xbd213df3,0x3df5bd15,0xbcf9bdf8,0xbd93bdd1,0x3c7bbdfe,0xbde23d71,0x3d5b3de7,0x3db93db1,0x3c173dff,0x3dc6bda2,0xbd98bdce,0xbdd8bd89,0xbd09bdf7,
0xbdb53d80,0x3c96bdfd,0xbd21bdf3,0x3d93bdd1,0x3da23dc6,0xbdac3dbe,0xbd093df7,0xbdef3d38,0xbc49bdff,0x3df8bcf9,0x3dc2bda7,0x3dfa3ce0,0xbd713de2,0xbdf1bd2c,0xbdfe3c7b,0xbdb1bdb9,
0x3db53d80,0xbd2c3df1,0x3ce03dfa,0xbdca3d9d,0xbd713de2,0x3dfd3c96,0x3deabd4f,0x3dc23da7,0x3df53d15,0xbbc9be00,0xbd93bdd1,0x3d7cbddf,0x3c49bdff,0xbdf83cf9,0xbdb13db9,0xbdf3bd21,
0xbdb53d80,0x3d84bddc,0xbc7bbdfe,0x3defbd38,0xbdffbc49,0xbd5bbde7,0xbde5bd66,0x3ce0bdfa,0xbda23dc6,0xbdfdbc96,0xbddf3d7c,0xbdb1bdb9,0x3d153df5,0xbdac3dbe,0xbc173dff,0xbdfc3caf,
0x3db53d80,0xbdac3dbe,0x3b493e00,0xbdff3c17,0xbd15bdf5,0xbd843ddc,0x3ce03dfa,0xbdf73d09,0xbd71bde2,0xbd2c3df1,0x3d4f3dea,0xbde53d66,0xbda2bdc6,0xbc963dfd,0x3d933dd1,0xbdca3d9d,
0xbdb53d80,0x3dcebd98,0x3c17bdff,0x3dfa3ce0,0x3dc6bda2,0x3e00bbc9,0x3d9dbdca,0x3db13db9,0x3dffbc49,0x3ddc3d84,0x3df3bd21,0x3caf3dfc,0x3de23d71,0x3d5b3de7,0x3df73d09,0xbd4f3dea,
0x3db53d80,0xbde73d5b,0xbcaf3dfc,0xbddfbd7c,0x3de23d71,0xbd98bdce,0xbe003b49,0x3d21bdf3,0xbd153df5,0x3dacbdbe,0xbce0bdfa,0x3dfe3c7b,0xbdffbc49,0x3ddc3d84,0x3deabd4f,0x3c173dff,
0xbdb53d80,0x3df8bcf9,0x3d09bdf7,0x3db13db9,0xbc493dff,0xbd2c3df1,0x3da73dc2,0xbdfc3caf,0xbdc6bda2,0xbd98bdce,0xbdfe3c7b,0x3d4fbdea,0x3df5bd15,0x3e00bbc9,0x3d66bde5,0x3d893dd8,
0x3db53d80,0xbe003bc9,0xbd383def,0xbd66bde5,0xbdf53d15,0x3df8bcf9,0x3cafbdfc,0x3d9d3dca,0x3de2bd71,0xbde73d5b,0x3b493e00,0xbdc2bda7,0xbdc63da2,0x3dcebd98,0xbce0bdfa,0x3ddf3d7c,
0xbdb53d80,0x3dfd3c96,0x3d66bde5,0x3caf3dfc,0xbda2bdc6,0xbdbebdac,0xbddf3d7c,0x3d4fbdea,0x3c493dff,0x3cf93df8,0x3dff3c17,0xbdd83d89,0x3d71bde2,0x3d2cbdf1,0xbdcabd9d,0x3e003b49,
0x3db53d80,0xbdf1bd2c,0xbd893dd8,0x3c7bbdfe,0x3d71bde2,0xbc963dfd,0x3def3d38,0xbdff3c17,0xbdf5bd15,0x3e00bbc9,0x3cafbdfc,0x3d093df7,0xbc493dff,0xbcf9bdf8,0xbe003b49,0x3de5bd66,
0xbdb53d80,0x3ddc3d84,0x3d9dbdca,0xbd4f3dea,0x3dff3c49,0x3de7bd5b,0xbd21bdf3,0x3d893dd8,0x3da2bdc6,0x3c96bdfd,0xbdf7bd09,0x3e003b49,0xbd15bdf5,0xbdbebdac,0xbdc23da7,0x3d93bdd1,
0x3db53d80,0xbdbebdac,0xbdb13db9,0x3da7bdc2,0x3d153df5,0xbddcbd84,0xbd893dd8,0x3d7cbddf,0x3d713de2,0xbdf1bd2c,0xbd383def,0x3d21bdf3,0x3da23dc6,0xbdfdbc96,0xbcaf3dfc,0x3c7bbdfe,
0xbdb53d80,0x3d983dce,0x3dc2bda7,0xbdd83d89,0xbdc63da2,0x3bc93e00,0x3dfebc7b,0xbe00bb49,0xbdff3c49,0xbd843ddc,0x3de53d66,0xbdd1bd93,0xbde2bd71,0xbde73d5b,0x3d7c3ddf,0xbd38bdef,
0x3db53d80,0xbd5bbde7,0xbdd13d93,0x3df7bd09,0xbde2bd71,0x3dcebd98,0xbdb9bdb1,0x3d663de5,0x3d15bdf5,0x3dbe3dac,0x3d89bdd8,0xbdca3d9d,0x3dff3c49,0xbd843ddc,0x3def3d38,0xbdc2bda7,
0xbdb53d80,0x3cf93df8,0x3ddfbd7c,0xbe00bb49,0x3c49bdff,0xbdf1bd2c,0xbc173dff,0x3d93bdd1,0x3dc63da2,0x3dcebd98,0xbdcabd9d,0x3d383def,0xbdf53d15,0x3bc93e00,0x3df3bd21,0xbdfabce0,
0x3db53d80,0xbbc9be00,0xbdea3d4f,0x3df33d21,0x3df5bd15,0x3cf93df8,0x3dd1bd93,0xbdfebc7b,0xbde23d71,0xbd5bbde7,0xbdb13db9,0x3dffbc17,0x3dc6bda2,0x3d983dce,0x3d89bdd8,0xbdf73d09,
0xbdb53d80,0xbc963dfd,0x3df3bd21,0xbdd1bd93,0x3da23dc6,0x3dacbdbe,0xbdf7bd09,0x3d383def,0xbc49bdff,0xbdf83cf9,0x3da73dc2,0x3ce0bdfa,0xbd713de2,0x3df13d2c,0xbc7bbdfe,0xbdb93db1,
0x3db53d80,0x3d2cbdf1,0xbdfa3ce0,0x3d9d3dca,0xbd713de2,0xbdfdbc96,0x3d4f3dea,0x3da7bdc2,0x3df53d15,0x3bc93e00,0x3dd1bd93,0xbddfbd7c,0x3c49bdff,0x3df8bcf9,0xbdb9bdb1,0xbd213df3,
0xbdb53d80,0xbd843ddc,0x3dfebc7b,0xbd38bdef,0xbdffbc49,0x3d5b3de7,0x3d66bde5,0xbdfabce0,0xbda23dc6,0x3dfd3c96,0xbd7cbddf,0xbdb93db1,0x3d153df5,0x3dacbdbe,0xbdffbc17,0x3caf3dfc,
0x3db53d80,0x3dacbdbe,0xbe003b49,0x3c173dff,0xbd15bdf5,0x3d84bddc,0xbdfa3ce0,0x3d093df7,0xbd71bde2,0x3d2cbdf1,0xbdea3d4f,0x3d663de5,0xbda2bdc6,0x3c96bdfd,0xbdd13d93,0x3d9d3dca,
0xbdb53d80,0xbdce3d98,0x3dff3c17,0x3ce0bdfa,0x3dc6bda2,0xbe003bc9,0x3dca3d9d,0x3db9bdb1,0x3dffbc49,0xbddcbd84,0x3d213df3,0x3dfcbcaf,0x3de23d71,0xbd5bbde7,0xbd093df7,0x3dea3d4f,
0x3db53d80,0x3de7bd5b,0xbdfcbcaf,0xbd7c3ddf,0x3de23d71,0x3d983dce,0xbb49be00,0xbdf3bd21,0xbd153df5,0xbdac3dbe,0x3dfabce0,0x3c7bbdfe,0xbdffbc49,0xbddcbd84,0x3d4f3dea,0x3dffbc17,
0xbdb53d80,0xbdf83cf9,0x3df73d09,0x3db9bdb1,0xbc493dff,0x3d2cbdf1,0xbdc23da7,0x3caf3dfc,0xbdc6bda2,0x3d983dce,0xbc7bbdfe,0xbdeabd4f,0x3df5bd15,0xbe003bc9,0x3de53d66,0x3dd8bd89,
0x3db53d80,0x3e00bbc9,0xbdefbd38,0xbde53d66,0xbdf53d15,0xbdf83cf9,0x3dfc3caf,0x3dcabd9d,0x3de2bd71,0x3de7bd5b,0xbe003b49,0xbda73dc2,0xbdc63da2,0xbdce3d98,0x3dfabce0,0x3d7cbddf,
0xbdb53d80,0xbdfdbc96,0x3de53d66,0x3dfcbcaf,0xbda2bdc6,0x3dbe3dac,0xbd7cbddf,0xbdeabd4f,0x3c493dff,0xbcf9bdf8,0xbc173dff,0x3d893dd8,0x3d71bde2,0xbd2c3df1,0x3d9dbdca,0x3b49be00,
0x3db53d80,0x3df13d2c,0xbdd8bd89,0xbdfebc7b,0x3d71bde2,0x3c96bdfd,0xbd383def,0x3c173dff,0xbdf5bd15,0xbe003bc9,0x3dfc3caf,0x3df7bd09,0xbc493dff,0x3cf93df8,0xbb49be00,0xbd66bde5,
0xbdb53d80,0xbddcbd84,0x3dca3d9d,0x3dea3d4f,0x3dff3c49,0xbde73d5b,0x3df3bd21,0x3dd8bd89,0x3da2bdc6,0xbc963dfd,0x3d09bdf7,0x3b49be00,0xbd15bdf5,0x3dbe3dac,0xbda7bdc2,0xbdd1bd93,
0x3db53d80,0x3dbe3dac,0xbdb9bdb1,0xbdc2bda7,0x3d153df5,0x3ddc3d84,0xbdd8bd89,0xbddfbd7c,0x3d713de2,0x3df13d2c,0xbdefbd38,0xbdf3bd21,0x3da23dc6,0x3dfd3c96,0xbdfcbcaf,0xbdfebc7b,
0x3f800000,0x0,0x3f800000,0x0,0x3f800000,0x0,0x3f800000,0x0,0x3f800000,0x0,0x3f800000,0x0,0x3f800000,0x0,0x3f800000,0x0,
0x3f800000,0x0,0x3f7ffb11,0xbc490e90,0x3f7fec43,0xbcc90ab0,0x3f7fd397,0xbd16c32c,0x3f7fb10f,0xbd48fb30,0x3f7f84ab,0xbd7b2b74,0x3f7f4e6d,0xbd96a905,0x3f7f0e58,0xbdafb680,
0x3f800000,0x0,0x3f7fec43,0xbcc90ab0,0x3f7fb10f,0xbd48fb30,0x3f7f4e6d,0xbd96a905,0x3f7ec46d,0xbdc8bd36,0x3f7e1324,0xbdfab273,0x3f7d3aac,0xbe164083,0x3f7c3b28,0xbe2f10a2,
0x3f800000,0x0,0x3f7fd397,0xbd16c32c,0x3f7f4e6d,0xbd96a905,0x3f7e70b0,0xbde1bc2e,0x3f7d3aac,0xbe164083,0x3f7baccd,0xbe3b6ecf,0x3f79c79d,0xbe605c13,0x3f778bc5,0xbe827dc0,
0x3f800000,0x0,0x3f7fb10f,0xbd48fb30,0x3f7ec46d,0xbdc8bd36,0x3f7d3aac,0xbe164083,0x3f7b14be,0xbe47c5c2,0x3f7853f8,0xbe78cfcc,0x3f74fa0b,0xbe94a031,0x3f710908,0xbeac7cd4,
0x3f800000,0x0,0x3f7f84ab,0xbd7b2b74,0x3f7e1324,0xbdfab273,0x3f7baccd,0xbe3b6ecf,0x3f7853f8,0xbe78cfcc,0x3f740bdd,0xbe9aa086,0x3f6ed89e,0xbeb8442a,0x3f68bf3c,0xbed53641,
0x3f800000,0x0,0x3f7f4e6d,0xbd96a905,0x3f7d3aac,0xbe164083,0x3f79c79d,0xbe605c13,0x3f74fa0b,0xbe94a031,0x3f6ed89e,0xbeb8442a,0x3f676bd8,0xbedae880,0x3f5ebe05,0xbefc5d27,
0x3f800000,0x0,0x3f7f0e58,0xbdafb680,0x3f7c3b28,0xbe2f10a2,0x3f778bc5,0xbe827dc0,0x3f710908,0xbeac7cd4,0x3f68bf3c,0xbed53641,0x3f5ebe05,0xbefc5d27,0x3f531849,0xbf10d3cd,
0x3f800000,0x0,0x3f7b14be,0xbe47c5c2,0x3f6c835e,0xbec3ef15,0x3f54db31,0xbf0e39da,0x3f3504f3,0xbf3504f3,0x3f0e39da,0xbf54db31,0x3ec3ef15,0xbf6c835e,0x3e47c5c2,0xbf7b14be,
0x3f800000,0x0,0x3f7a7302,0xbe541501,0x3f6a09a7,0xbecf7bca,0x3f4f7a1f,0xbf15f6d9,0x3f2beb4a,0xbf3daef9,0x3f00e7e4,0xbf5d2d53,0x3ea09ae5,0xbf731447,0x3de1bc2e,0xbf7e70b0,
0x3f800000,0x0,0x3f79c79d,0xbe605c13,0x3f676bd8,0xbedae880,0x3f49d112,0xbf1d7fd1,0x3f226799,0xbf45e403,0x3ee63375,0xbf64aa59,0x3e78cfcc,0xbf7853f8,0x3cc90ab0,0xbf7fec43,
0x3f800000,0x0,0x3f791298,0xbe6c9a7f,0x3f64aa59,0xbee63375,0x3f43e200,0xbf24d225,0x3f187fc0,0xbf4d9f02,0x3ec9b953,0xbf6b4b0c,0x3e2f10a2,0xbf7c3b28,0xbd7b2b74,0xbf7f84ab,
0x3f800000,0x0,0x3f7853f8,0xbe78cfcc,0x3f61c598,0xbef15aea,0x3f3daef9,0xbf2beb4a,0x3f0e39da,0xbf54db31,0x3eac7cd4,0xbf710908,0x3dc8bd36,0xbf7ec46d,0xbe164083,0xbf7d3aac,
0x3f800000,0x0,0x3f778bc5,0xbe827dc0,0x3f5ebe05,0xbefc5d27,0x3f373a23,0xbf32c8c9,0x3f039c3d,0xbf5b941a,0x3e8e9a22,0xbf75dec6,0x3cc90ab0,0xbf7fec43,0xbe6c9a7f,0xbf791298,
0x3f800000,0x0,0x3f76ba07,0xbe888e93,0x3f5b941a,0xbf039c3d,0x3f3085bb,0xbf396842,0x3ef15aea,0xbf61c598,0x3e605c13,0xbf79c79d,0xbd48fb30,0xbf7fb10f,0xbea09ae5,0xbf731447,
0x3f800000,0x0,0x3f75dec6,0xbe8e9a22,0x3f584853,0xbf08f59b,0x3f299415,0xbf3fc767,0x3edae880,0xbf676bd8,0x3e22abb6,0xbf7cbfc9,0xbdfab273,0xbf7e1324,0xbec9b953,0xbf6b4b0c,
0x3f800000,0x0,0x3f7ec46d,0xbdc8bd36,0x3f7b14be,0xbe47c5c2,0x3f74fa0b,0xbe94a031,0x3f6c835e,0xbec3ef15,0x3f61c598,0xbef15aea,0x3f54db31,0xbf0e39da,0x3f45e403,0xbf226799,
0x3f800000,0x0,0x3f6b4b0c,0xbec9b953,0x3f3085bb,0xbf396842,0x3eb263ef,0xbf6ff573,0xbd48fb30,0xbf7fb10f,0xbee0924f,0xbf660f88,0xbf41d870,0xbf273656,0xbf740bdd,0xbe9aa086,
0x3f800000,0x0,0x3f6a09a7,0xbecf7bca,0x3f2beb4a,0xbf3daef9,0x3ea09ae5,0xbf731447,0xbdc8bd36,0xbf7ec46d,0xbefc5d27,0xbf5ebe05,0xbf4d9f02,0xbf187fc0,0xbf79c79d,0xbe605c13,
0x3f800000,0x0,0x3f68bf3c,0xbed53641,0x3f273656,0xbf41d870,0x3e8e9a22,0xbf75dec6,0xbe164083,0xbf7d3aac,0xbf0b9a6b,0xbf5695e5,0xbf584853,0xbf08f59b,0xbf7dabcc,0xbe09cf86,
0x3f800000,0x0,0x3f676bd8,0xbedae880,0x3f226799,0xbf45e403,0x3e78cfcc,0xbf7853f8,0xbe47c5c2,0xbf7b14be,0xbf187fc0,0xbf4d9f02,0xbf61c598,0xbef15aea,0xbf7fb10f,0xbd48fb30,
0x3f800000,0x0,0x3f660f88,0xbee0924f,0x3f1d7fd1,0xbf49d112,0x3e541501,0xbf7a7302,0xbe78cfcc,0xbf7853f8,0xbf24d225,0xbf43e200,0xbf6a09a7,0xbecf7bca,0xbf7fd397,0x3d16c32c,
0x3f800000,0x0,0x3f64aa59,0xbee63375,0x3f187fc0,0xbf4d9f02,0x3e2f10a2,0xbf7c3b28,0xbe94a031,0xbf74fa0b,0xbf3085bb,0xbf396842,0xbf710908,0xbeac7cd4,0xbf7e1324,0x3dfab273,
0x3f800000,0x0,0x3f633c5a,0xbeebcbbb,0x3f13682a,0xbf514d3d,0x3e09cf86,0xbf7dabcc,0xbeac7cd4,0xbf710908,0xbf3b8f3b,0xbf2e3bde,0xbf76ba07,0xbe888e93,0xbf7a7302,0x3e541501,
0x3f800000,0x0,0x3f74fa0b,0xbe94a031,0x3f54db31,0xbf0e39da,0x3f226799,0xbf45e403,0x3ec3ef15,0xbf6c835e,0x3dc8bd36,0xbf7ec46d,0xbe47c5c2,0xbf7b14be,0xbef15aea,0xbf61c598,
0x3f800000,0x0,0x3f531849,0xbf10d3cd,0x3eb8442a,0xbf6ed89e,0xbe6c9a7f,0xbf791298,0xbf3daef9,0xbf2beb4a,0xbf7dabcc,0xbe09cf86,0xbf64aa59,0x3ee63375,0xbef6e0cb,0x3f604621,
0x3f800000,0x0,0x3f514d3d,0xbf13682a,0x3eac7cd4,0xbf710908,0xbe888e93,0xbf76ba07,0xbf45e403,0xbf226799,0xbf7f4e6d,0xbd96a905,0xbf5b941a,0x3f039c3d,0xbecf7bca,0x3f6a09a7,
0x3f800000,0x0,0x3f4f7a1f,0xbf15f6d9,0x3ea09ae5,0xbf731447,0xbe9aa086,0xbf740bdd,0xbf4d9f02,0xbf187fc0,0xbf7ffb11,0xbc490e90,0xbf514d3d,0x3f13682a,0xbea68f12,0x3f721352,
0x3f800000,0x0,0x3f4d9f02,0xbf187fc0,0x3e94a031,0xbf74fa0b,0xbeac7cd4,0xbf710908,0xbf54db31,0xbf0e39da,0xbf7fb10f,0x3d48fb30,0xbf45e403,0x3f226799,0xbe78cfcc,0x3f7853f8,
0x3f800000,0x0,0x3f4bbbf8,0xbf1b02c6,0x3e888e93,0xbf76ba07,0xbebe1d4a,0xbf6db293,0xbf5b941a,0xbf039c3d,0xbf7e70b0,0x3de1bc2e,0xbf396842,0x3f3085bb,0xbe22abb6,0x3f7cbfc9,
0x3f800000,0x0,0x3f49d112,0xbf1d7fd1,0x3e78cfcc,0xbf7853f8,0xbecf7bca,0xbf6a09a7,0xbf61c598,0xbef15aea,0xbf7c3b28,0x3e2f10a2,0xbf2beb4a,0x3f3daef9,0xbd96a905,0x3f7f4e6d,
0x3f800000,0x0,0x3f47de65,0xbf1ff6cb,0x3e605c13,0xbf79c79d,0xbee0924f,0xbf660f88,0xbf676bd8,0xbedae880,0xbf791298,0x3e6c9a7f,0xbf1d7fd1,0x3f49d112,0x3c490e90,0x3f7ffb11,
0x3f800000,0x0,0x3f800000,0x0,0x3f800000,0x0,0x3f800000,0x0,0x40000000,0x0,0x3f800000,0x0,0x3f800000,0x0,0x3f800000,0x0,
0x3f800000,0x0,0x3f7ffb11,0xbc490e90,0x3f7fec43,0xbcc90ab0,0x3f7fd397,0xbd16c32c,0x3fffb10f,0xbdc8fb30,0x3f7f84ab,0xbd7b2b74,0x3f7f4e6d,0xbd96a905,0x3f7f0e58,0xbdafb680,
0x3f800000,0x0,0x3f7fec43,0xbcc90ab0,0x3f7fb10f,0xbd48fb30,0x3f7f4e6d,0xbd96a905,0x3ffec46d,0xbe48bd36,0x3f7e1324,0xbdfab273,0x3f7d3aac,0xbe164083,0x3f7c3b28,0xbe2f10a2,
0x3f800000,0x0,0x3f7fd397,0xbd16c32c,0x3f7f4e6d,0xbd96a905,0x3f7e70b0,0xbde1bc2e,0x3ffd3aac,0xbe964083,0x3f7baccd,0xbe3b6ecf,0x3f79c79d,0xbe605c13,0x3f778bc5,0xbe827dc0,
0x3f800000,0x0,0x3f7fb10f,0xbd48fb30,0x3f7ec46d,0xbdc8bd36,0x3f7d3aac,0xbe164083,0x3ffb14be,0xbec7c5c2,0x3f7853f8,0xbe78cfcc,0x3f74fa0b,0xbe94a031,0x3f710908,0xbeac7cd4,
0x3f800000,0x0,0x3f7f84ab,0xbd7b2b74,0x3f7e1324,0xbdfab273,0x3f7baccd,0xbe3b6ecf,0x3ff853f8,0xbef8cfcc,0x3f740bdd,0xbe9aa086,0x3f6ed89e,0xbeb8442a,0x3f68bf3c,0xbed53641,
0x3f800000,0x0,0x3f7f4e6d,0xbd96a905,0x3f7d3aac,0xbe164083,0x3f79c79d,0xbe605c13,0x3ff4fa0b,0xbf14a031,0x3f6ed89e,0xbeb8442a,0x3f676bd8,0xbedae880,0x3f5ebe05,0xbefc5d27,
0x3f800000,0x0,0x3f7f0e58,0xbdafb680,0x3f7c3b28,0xbe2f10a2,0x3f778bc5,0xbe827dc0,0x3ff10908,0xbf2c7cd4,0x3f68bf3c,0xbed53641,0x3f5ebe05,0xbefc5d27,0x3f531849,0xbf10d3cd,
0x3f800000,0x0,0x3f7ec46d,0xbdc8bd36,0x3f7b14be,0xbe47c5c2,0x3f74fa0b,0xbe94a031,0x3fec835e,0xbf43ef15,0x3f61c598,0xbef15aea,0x3f54db31,0xbf0e39da,0x3f45e403,0xbf226799,
0x3f800000,0x0,0x3f7e70b0,0xbde1bc2e,0x3f79c79d,0xbe605c13,0x3f721352,0xbea68f12,0x3fe76bd8,0xbf5ae880,0x3f59f26a,0xbf064b82,0x3f49d112,0xbf1d7fd1,0x3f373a23,0xbf32c8c9,
0x3f800000,0x0,0x3f7e1324,0xbdfab273,0x3f7853f8,0xbe78cfcc,0x3f6ed89e,0xbeb8442a,0x3fe1c598,0xbf715aea,0x3f514d3d,0xbf13682a,0x3f3daef9,0xbf2beb4a,0x3f273656,0xbf41d870,
0x3f800000,0x0,0x3f7dabcc,0xbe09cf86,0x3f76ba07,0xbe888e93,0x3f6b4b0c,0xbec9b953,0x3fdb941a,0xbf839c3d,0x3f47de65,0xbf1ff6cb,0x3f3085bb,0xbf396842,0x3f15f6d9,0xbf4f7a1f,
0x3f800000,0x0,0x3f7d3aac,0xbe164083,0x3f74fa0b,0xbe94a031,0x3f676bd8,0xbedae880,0x3fd4db31,0xbf8e39da,0x3f3daef9,0xbf2beb4a,0x3f226799,0xbf45e403,0x3f039c3d,0xbf5b941a,
0x3f800000,0x0,0x3f7cbfc9,0xbe22abb6,0x3f731447,0xbea09ae5,0x3f633c5a,0xbeebcbbb,0x3fcd9f02,0xbf987fc0,0x3f32c8c9,0xbf373a23,0x3f13682a,0xbf514d3d,0x3ee0924f,0xbf660f88,
0x3f800000,0x0,0x3f7c3b28,0xbe2f10a2,0x3f710908,0xbeac7cd4,0x3f5ebe05,0xbefc5d27,0x3fc5e403,0xbfa26799,0x3f273656,0xbf41d870,0x3f039c3d,0xbf5b941a,0x3eb8442a,0xbf6ed89e,
0x3f800000,0x0,0x3f7baccd,0xbe3b6ecf,0x3f6ed89e,0xbeb8442a,0x3f59f26a,0xbf064b82,0x3fbdaef9,0xbfabeb4a,0x3f1b02c6,0xbf4bbbf8,0x3ee63375,0xbf64aa59,0x3e8e9a22,0xbf75dec6,
0x3f800000,0x0,0x3f7b14be,0xbe47c5c2,0x3f6c835e,0xbec3ef15,0x3f54db31,0xbf0e39da,0x3fb504f3,0xbfb504f3,0x3f0e39da,0xbf54db31,0x3ec3ef15,0xbf6c835e,0x3e47c5c2,0xbf7b14be,
0x3f800000,0x0,0x3f7a7302,0xbe541501,0x3f6a09a7,0xbecf7bca,0x3f4f7a1f,0xbf15f6d9,0x3fabeb4a,0xbfbdaef9,0x3f00e7e4,0xbf5d2d53,0x3ea09ae5,0xbf731447,0x3de1bc2e,0xbf7e70b0,
0x3f800000,0x0,0x3f79c79d,0xbe605c13,0x3f676bd8,0xbedae880,0x3f49d112,0xbf1d7fd1,0x3fa26799,0xbfc5e403,0x3ee63375,0xbf64aa59,0x3e78cfcc,0xbf7853f8,0x3cc90ab0,0xbf7fec43,
0x3f800000,0x0,0x3f791298,0xbe6c9a7f,0x3f64aa59,0xbee63375,0x3f43e200,0xbf24d225,0x3f987fc0,0xbfcd9f02,0x3ec9b953,0xbf6b4b0c,0x3e2f10a2,0xbf7c3b28,0xbd7b2b74,0xbf7f84ab,
0x3f800000,0x0,0x3f7853f8,0xbe78cfcc,0x3f61c598,0xbef15aea,0x3f3daef9,0xbf2beb4a,0x3f8e39da,0xbfd4db31,0x3eac7cd4,0xbf710908,0x3dc8bd36,0xbf7ec46d,0xbe164083,0xbf7d3aac,
0x3f800000,0x0,0x3f778bc5,0xbe827dc0,0x3f5ebe05,0xbefc5d27,0x3f373a23,0xbf32c8c9,0x3f839c3d,0xbfdb941a,0x3e8e9a22,0xbf75dec6,0x3cc90ab0,0xbf7fec43,0xbe6c9a7f,0xbf791298,
0x3f800000,0x0,0x3f76ba07,0xbe888e93,0x3f5b941a,0xbf039c3d,0x3f3085bb,0xbf396842,0x3f715aea,0xbfe1c598,0x3e605c13,0xbf79c79d,0xbd48fb30,0xbf7fb10f,0xbea09ae5,0xbf731447,
0x3f800000,0x0,0x3f75dec6,0xbe8e9a22,0x3f584853,0xbf08f59b,0x3f299415,0xbf3fc767,0x3f5ae880,0xbfe76bd8,0x3e22abb6,0xbf7cbfc9,0xbdfab273,0xbf7e1324,0xbec9b953,0xbf6b4b0c,
0x3f800000,0x0,0x3f74fa0b,0xbe94a031,0x3f54db31,0xbf0e39da,0x3f226799,0xbf45e403,0x3f43ef15,0xbfec835e,0x3dc8bd36,0xbf7ec46d,0xbe47c5c2,0xbf7b14be,0xbef15aea,0xbf61c598,
0x3f800000,0x0,0x3f740bdd,0xbe9aa086,0x3f514d3d,0xbf13682a,0x3f1b02c6,0xbf4bbbf8,0x3f2c7cd4,0xbff10908,0x3d16c32c,0xbf7fd397,0xbe888e93,0xbf76ba07,0xbf0b9a6b,0xbf5695e5,
0x3f800000,0x0,0x3f731447,0xbea09ae5,0x3f4d9f02,0xbf187fc0,0x3f13682a,0xbf514d3d,0x3f14a031,0xbff4fa0b,0xbcc90ab0,0xbf7fec43,0xbeac7cd4,0xbf710908,0xbf1d7fd1,0xbf49d112,
0x3f800000,0x0,0x3f721352,0xbea68f12,0x3f49d112,0xbf1d7fd1,0x3f0b9a6b,0xbf5695e5,0x3ef8cfcc,0xbff853f8,0xbdafb680,0xbf7f0e58,0xbecf7bca,0xbf6a09a7,0xbf2e3bde,0xbf3b8f3b,
0x3f800000,0x0,0x3f710908,0xbeac7cd4,0x3f45e403,0xbf226799,0x3f039c3d,0xbf5b941a,0x3ec7c5c2,0xbffb14be,0xbe164083,0xbf7d3aac,0xbef15aea,0xbf61c598,0xbf3daef9,0xbf2beb4a,
0x3f800000,0x0,0x3f6ff573,0xbeb263ef,0x3f41d870,0xbf273656,0x3ef6e0cb,0xbf604621,0x3e964083,0xbffd3aac,0xbe541501,0xbf7a7302,0xbf08f59b,0xbf584853,0xbf4bbbf8,0xbf1b02c6,
0x3f800000,0x0,0x3f6ed89e,0xbeb8442a,0x3f3daef9,0xbf2beb4a,0x3ee63375,0xbf64aa59,0x3e48bd36,0xbffec46d,0xbe888e93,0xbf76ba07,0xbf187fc0,0xbf4d9f02,0xbf584853,0xbf08f59b,
0x3f800000,0x0,0x3f6db293,0xbebe1d4a,0x3f396842,0xbf3085bb,0x3ed53641,0xbf68bf3c,0x3dc8fb30,0xbfffb10f,0xbea68f12,0xbf721352,0xbf273656,0xbf41d870,0xbf633c5a,0xbeebcbbb,
0x3f800000,0x0,0x3f7fffb1,0xbb490fc6,0x3f7ffec4,0xbbc90f88,0x3f7ffd39,0xbc16cb58,0x3ffffb11,0xbcc90e90,0x3f7ff84a,0xbc7b514b,0x3f7ff4e6,0xbc96c9b6,0x3f7ff0e3,0xbcafea69,
0x3f800000,0x0,0x3f7ff84a,0xbc7b514b,0x3f7fe129,0xbcfb49ba,0x3f7fba9e,0xbd3c6dd5,0x3fff84ab,0xbdfb2b74,0x3f7f3f54,0xbd9cecf9,0x3f7eea9d,0xbdbc3ac3,0x3f7e868b,0xbddb7d37,
0x3f800000,0x0,0x3f7fe705,0xbce22a7a,0x3f7f9c18,0xbd621469,0x3f7f1f49,0xbda973ba,0x3ffe70b0,0xbe61bc2e,0x3f7d906e,0xbe0cec4a,0x3f7c7eb0,0xbe28defc,0x3f7b3bab,0xbe44b0b9,
0x3f800000,0x0,0x3f7fcbe2,0xbd2351cb,0x3f7f2f9d,0xbda3308c,0x3f7e2b72,0xbdf475c0,0x3ffcbfc9,0xbea2abb6,0x3f7aed37,0xbe4ada4f,0x3f78b47b,0xbe72b651,0x3f76167a,0xbe8d17c0,
0x3f800000,0x0,0x3f7fa6e3,0xbd55880e,0x3f7e9bc9,0xbdd53db9,0x3f7cdf6c,0xbe1f917b,0x3ffa7302,0xbed41501,0x3f77583a,0xbe840270,0x3f73913f,0xbe9d9e78,0x3f6f20b0,0xbeb6ccc3,
0x3f800000,0x0,0x3f7f7808,0xbd83db0a,0x3f7de0b1,0xbe039502,0x3f7b3bab,0xbe44b0b9,0x3ff78bc5,0xbf027dc0,0x3f72d4eb,0xbea21887,0x3f6d1c1d,0xbec1071e,0x3f666771,0xbedf28a9,
0x3f800000,0x0,0x3f7f3f54,0xbd9cecf9,0x3f7cfe73,0xbe1c76de,0x3f7940c0,0xbe698bba,0x3ff40bdd,0xbf1aa086,0x3f6d67a1,0xbebf926f,0x3f655e0b,0xbee363fa,0x3f5bfb34,0xbf02ef9f,
0x3f800000,0x0,0x3f7efcc9,0xbdb5f8da,0x3f7bf531,0xbe354098,0x3f76ef5b,0xbe870ada,0x3feff573,0xbf3263ef,0x3f671599,0xbedc53c1,0x3f5c61c7,0xbf0242b1,0x3f4fefa8,0xbf1553b7,
0x3f800000,0x0,0x3f7eb069,0xbdcefdb7,0x3f7ac516,0xbe4dee60,0x3f74484b,0xbe9920fe,0x3feb4b0c,0xbf49b953,0x3f5fe4e9,0xbef840c8,0x3f5233c6,0xbf121eb0,0x3f425b89,0xbf269de3,
0x3f800000,0x0,0x3f7e5a38,0xbde7fa9a,0x3f796e4e,0xbe667c66,0x3f714c7a,0xbeab0201,0x3fe60f88,0xbf60924f,0x3f57dc7f,0xbf099f4e,0x3f46e22a,0xbf212ff9,0x3f33587a,0xbf36ad7f,
0x3f800000,0x0,0x3f7dfa38,0xbe007745,0x3f77f110,0xbe7ee6e1,0x3f6dfcf2,0xbebca7af,0x3fe04621,0xbf76e0cb,0x3f4f0417,0xbf16999f,0x3f3a7ca4,0xbf2f61a5,0x3f2302d3,0xbf456439,
0x3f800000,0x0,0x3f7d906e,0xbe0cec4a,0x3f764d97,0xbe8b9507,0x3f6a5ad9,0xbece0bea,0x3fd9f26a,0xbf864b82,0x3f456439,0xbf2302d3,0x3f2d1469,0xbf3ca003,0x3f11796b,0xbf52a649,
0x3f800000,0x0,0x3f7d1cdd,0xbe195be0,0x3f748422,0xbe97a117,0x3f666771,0xbedf28a9,0x3fd31849,0xbf90d3cd,0x3f3b0629,0xbf2ecef7,0x3f1ebc12,0xbf48d8b3,0x3efdbabb,0xbf5e5aa6,
0x3f800000,0x0,0x3f7c9f8a,0xbe25c58c,0x3f7294f8,0xbea395c5,0x3f62241a,0xbeeff7fb,0x3fcbbbf8,0xbf9b02c6,0x3f2ff3e6,0xbf39f2ac,0x3f0f8784,0xbf53fac3,0x3ed6a399,0xbf686b39,
0x3f800000,0x0,0x3f7c187a,0xbe3228d4,0x3f708066,0xbeaf713a,0x3f5d924d,0xbf003a06,0x3fc3e200,0xbfa4d225,0x3f24381a,0xbf446337,0x3eff17b2,0xbf5df6be,0x3eadf73c,0xbf70c501,
0x3f800000,0x0,0x3f7b87b2,0xbe3e853e,0x3f6e46be,0xbebb31a0,0x3f58b3a1,0xbf084b92,0x3fbb8f3b,0xbfae3bde,0x3f17de12,0xbf4e1689,0x3eddbe79,0xbf66becc,0x3e840270,0xbf77583a,
0x3f800000,0x0,0x3f7aed37,0xbe4ada4f,0x3f6be858,0xbec6d529,0x3f5389c7,0xbf102dd5,0x3fb2c8c9,0xbfb73a23,0x3f0af1b7,0xbf570348,0x3ebb31a0,0xbf6e46be,0x3e3228d4,0xbf7c187a,
0x3f800000,0x0,0x3f7a4910,0xbe57278f,0x3f696591,0xbed25a09,0x3f4e1689,0xbf17de12,0x3fa99415,0xbfbfc767,0x3efafef7,0xbf5f20db,0x3e97a117,0xbf748422,0x3db5f8da,0xbf7efcc9,
0x3f800000,0x0,0x3f799b43,0xbe636c83,0x3f66becc,0xbeddbe79,0x3f485bca,0xbf1f599f,0x3f9ff6cb,0xbfc7de65,0x3edf28a9,0xbf666771,0x3e667c66,0xbf796e4e,0x3b490fc6,0xbf7fffb1,
0x3f800000,0x0,0x3f78e3d6,0xbe6fa8b2,0x3f63f473,0xbee900b7,0x3f425b89,0xbf269de3,0x3f95f6d9,0xbfcf7a1f,0x3ec27b55,0xbf6cd007,0x3e1c76de,0xbf7cfe73,0xbda973ba,0xbf7f1f49,
0x3f800000,0x0,0x3f7822d1,0xbe7bdba4,0x3f6106f2,0xbef41f07,0x3f3c17d9,0xbf2da859,0x3f8b9a6b,0xbfd695e5,0x3ea5129f,0xbf725470,0x3da3308c,0xbf7f2f9d,0xbe2bf804,0xbf7c5d3a,
0x3f800000,0x0,0x3f77583a,0xbe840270,0x3f5df6be,0xbeff17b2,0x3f3592e7,0xbf34768f,0x3f80e7e4,0xbfdd2d53,0x3e870ada,0xbf76ef5b,0x3bc90f88,0xbf7ffec4,0xbe80f8c0,0xbf77beb7,
0x3f800000,0x0,0x3f76841b,0xbe8a11f7,0x3f5ac450,0xbf04f484,0x3f2ecef7,0xbf3b0629,0x3f6bcbbb,0xbfe33c5a,0x3e5101f1,0xbf7a9c59,0xbd8a200a,0xbf7f6ac7,0xbeab0201,0xbf714c7a,
0x3f800000,0x0,0x3f75a67b,0xbe901c2c,0x3f577026,0xbf0a48ad,0x3f27ce61,0xbf4154e1,0x3f553641,0xbfe8bf3c,0x3e1324ca,0xbf7d57de,0xbe1008b7,0xbf7d7474,0xbed3c867,0xbf6912ae,
0x3f800000,0x0,0x3f74bf62,0xbe9620d2,0x3f53fac3,0xbf0f8784,0x3f209393,0xbf476085,0x3f3e1d4a,0xbfedb293,0x3da973ba,0xbf7f1f49,0xbe5a3997,0xbf7a1e84,0xbefafef7,0xbf5f20db,
0x3f800000,0x0,0x3f73ced9,0xbe9c1faf,0x3f5064af,0xbf14b039,0x3f19210f,0xbf4d26fd,0x3f268f12,0xbff21352,0x3cafea69,0xbf7ff0e3,0xbe919ddd,0xbf756d97,0xbf102dd5,0xbf5389c7,
0x3f800000,0x0,0x3f72d4eb,0xbea21887,0x3f4cae79,0xbf19c200,0x3f11796b,0xbf52a649,0x3f0e9a22,0xbff5dec6,0xbd2351cb,0xbf7fcbe2,0xbeb554ec,0xbf6f6830,0xbf21cbfb,0xbf466354,
0x3f800000,0x0,0x3f71d19f,0xbea80b1f,0x3f48d8b3,0xbf1ebc12,0x3f099f4e,0xbf57dc7f,0x3eec9a7f,0xbff91298,0xbdcefdb7,0xbf7eb069,0xbed8106b,0xbf6816a8,0xbf3238aa,0xbf37c655,
0x3f800000,0x0,0x3f70c501,0xbeadf73c,0x3f44e3f5,0xbf239da9,0x3f019573,0xbf5cc7d1,0x3ebb6ecf,0xbffbaccd,0xbe25c58c,0xbf7c9f8a,0xbef9a02d,0xbf5f8327,0xbf4154e1,0xbf27ce61,
0x3f800000,0x0,0x3f6faf1b,0xbeb3dca5,0x3f40d0da,0xbf286605,0x3ef2bd43,0xbf61668a,0x3e89cf86,0xbffdabcc,0xbe636c83,0xbf799b43,0xbf0cead0,0xbf55b993,0xbf4f0417,0xbf16999f,
0x3f800000,0x0,0x3f6e8ff8,0xbeb9bb1e,0x3f3ca003,0xbf2d1469,0x3ee1fb6a,0xbf65b710,0x3e2fb680,0xbfff0e58,0xbe901c2c,0xbf75a67b,0xbf1c420c,0xbf4ac77f,0xbf5b2c79,0xbf044889,
0x3f800000,0x0,0x3f6d67a1,0xbebf926f,0x3f385216,0xbf31a81d,0x3ed0eb2a,0xbf69b7e4,0x3d96c32c,0xbfffd397,0xbeadf73c,0xbf70c501,0xbf2ac082,0xbf3ebc1b,0xbf65b710,0xbee1fb6a,
0x3f800000,0x0,0x3f7ffec4,0xbbc90f88,0x3f7ffb11,0xbc490e90,0x3f7ff4e6,0xbc96c9b6,0x3fffec43,0xbd490ab0,0x3f7fe129,0xbcfb49ba,0x3f7fd397,0xbd16c32c,0x3f7fc38f,0xbd2fe007,
0x3f800000,0x0,0x3f7ff4e6,0xbc96c9b6,0x3f7fd397,0xbd16c32c,0x3f7f9c18,0xbd621469,0x3fff4e6d,0xbe16a905,0x3f7eea9d,0xbdbc3ac3,0x3f7e70b0,0xbde1bc2e,0x3f7de0b1,0xbe039502,
0x3f800000,0x0,0x3f7fe129,0xbcfb49ba,0x3f7f84ab,0xbd7b2b74,0x3f7eea9d,0xbdbc3ac3,0x3ffe1324,0xbe7ab273,0x3f7cfe73,0xbe1c76de,0x3f7baccd,0xbe3b6ecf,0x3f7a1e84,0xbe5a3997,
0x3f800000,0x0,0x3f7fc38f,0xbd2fe007,0x3f7f0e58,0xbdafb680,0x3f7de0b1,0xbe039502,0x3ffc3b28,0xbeaf10a2,0x3f7a1e84,0xbe5a3997,0x3f778bc5,0xbe827dc0,0x3f748422,0xbe97a117,
0x3f800000,0x0,0x3f7f9c18,0xbd621469,0x3f7e70b0,0xbde1bc2e,0x3f7c7eb0,0xbe28defc,0x3ff9c79d,0xbee05c13,0x3f764d97,0xbe8b9507,0x3f721352,0xbea68f12,0x3f6d1c1d,0xbec1071e,
0x3f800000,0x0,0x3f7f6ac7,0xbd8a200a,0x3f7dabcc,0xbe09cf86,0x3f7ac516,0xbe4dee60,0x3ff6ba07,0xbf088e93,0x3f718f57,0xbea986c4,0x3f6b4b0c,0xbec9b953,0x3f63f473,0xbee900b7,
0x3f800000,0x0,0x3f7f2f9d,0xbda3308c,0x3f7cbfc9,0xbe22abb6,0x3f78b47b,0xbe72b651,0x3ff31447,0xbf209ae5,0x3f6be858,0xbec6d529,0x3f633c5a,0xbeebcbbb,0x3f591e6a,0xbf07a136,
0x3f800000,0x0,0x3f7eea9d,0xbdbc3ac3,0x3f7baccd,0xbe3b6ecf,0x3f764d97,0xbe8b9507,0x3feed89e,0xbf38442a,0x3f655e0b,0xbee363fa,0x3f59f26a,0xbf064b82,0x3f4cae79,0xbf19c200,
0x3f800000,0x0,0x3f7e9bc9,0xbdd53db9,0x3f7a7302,0xbe541501,0x3f73913f,0xbe9d9e78,0x3fea09a7,0xbf4f7bca,0x3f5df6be,0xbeff17b2,0x3f4f7a1f,0xbf15f6d9,0x3f3ebc1b,0xbf2ac082,
0x3f800000,0x0,0x3f7e4323,0xbdee3876,0x3f791298,0xbe6c9a7f,0x3f708066,0xbeaf713a,0x3fe4aa59,0xbf663375,0x3f55b993,0xbf0cead0,0x3f43e200,0xbf24d225,0x3f2f61a5,0xbf3a7ca4,
0x3f800000,0x0,0x3f7de0b1,0xbe039502,0x3f778bc5,0xbe827dc0,0x3f6d1c1d,0xbec1071e,0x3fdebe05,0xbf7c5d27,0x3f4cae79,0xbf19c200,0x3f373a23,0xbf32c8c9,0x3f1ebc12,0xbf48d8b3,
0x3f800000,0x0,0x3f7d7474,0xbe1008b7,0x3f75dec6,0xbe8e9a22,0x3f696591,0xbed25a09,0x3fd84853,0xbf88f59b,0x3f42de29,0xbf26050a,0x3f299415,0xbf3fc767,0x3f0cead0,0xbf55b993,
0x3f800000,0x0,0x3f7cfe73,0xbe1c76de,0x3f740bdd,0xbe9aa086,0x3f655e0b,0xbee363fa,0x3fd14d3d,0xbf93682a,0x3f385216,0xbf31a81d,0x3f1b02c6,0xbf4bbbf8,0x3ef41f07,0xbf6106f2,
0x3f800000,0x0,0x3f7c7eb0,0xbe28defc,0x3f721352,0xbea68f12,0x3f6106f2,0xbef41f07,0x3fc9d112,0xbf9d7fd1,0x3f2d1469,0xbf3ca003,0x3f0b9a6b,0xbf5695e5,0x3ecc9b8b,0xbf6aab7b,
0x3f800000,0x0,0x3f7bf531,0xbe354098,0x3f6ff573,0xbeb263ef,0x3f5c61c7,0xbf0242b1,0x3fc1d870,0xbfa73656,0x3f212ff9,0xbf46e22a,0x3ef6e0cb,0xbf604621,0x3ea395c5,0xbf7294f8,
0x3f800000,0x0,0x3f7b61fc,0xbe419b37,0x3f6db293,0xbebe1d4a,0x3f577026,0xbf0a48ad,0x3fb96842,0xbfb085bb,0x3f14b039,0xbf5064af,0x3ed53641,0xbf68bf3c,0x3e72b651,0xbf78b47b,
0x3f800000,0x0,0x3f7ac516,0xbe4dee60,0x3f6b4b0c,0xbec9b953,0x3f5233c6,0xbf121eb0,0x3fb085bb,0xbfb96842,0x3f07a136,0xbf591e6a,0x3eb263ef,0xbf6ff573,0x3e1c76de,0xbf7cfe73,
0x3f800000,0x0,0x3f7a1e84,0xbe5a3997,0x3f68bf3c,0xbed53641,0x3f4cae79,0xbf19c200,0x3fa73656,0xbfc1d870,0x3ef41f07,0xbf6106f2,0x3e8e9a22,0xbf75dec6,0x3d8a200a,0xbf7f6ac7,
0x3f800000,0x0,0x3f796e4e,0xbe667c66,0x3f660f88,0xbee0924f,0x3f46e22a,0xbf212ff9,0x3f9d7fd1,0xbfc9d112,0x3ed8106b,0xbf6816a8,0x3e541501,0xbf7a7302,0xbc96c9b6,0xbf7ff4e6,
0x3f800000,0x0,0x3f78b47b,0xbe72b651,0x3f633c5a,0xbeebcbbb,0x3f40d0da,0xbf286605,0x3f93682a,0xbfd14d3d,0x3ebb31a0,0xbf6e46be,0x3e09cf86,0xbf7dabcc,0xbdd53db9,0xbf7e9bc9,
0x3f800000,0x0,0x3f77f110,0xbe7ee6e1,0x3f604621,0xbef6e0cb,0x3f3a7ca4,0xbf2f61a5,0x3f88f59b,0xbfd84853,0x3e9d9e78,0xbf73913f,0x3d7b2b74,0xbf7f84ab,0xbe419b37,0xbf7b61fc,
0x3f800000,0x0,0x3f772417,0xbe8586ce,0x3f5d2d53,0xbf00e7e4,0x3f33e7bc,0xbf36206c,0x3f7c5d27,0xbfdebe05,0x3e7ee6e1,0xbf77f110,0xbc490e90,0xbf7ffb11,0xbe8b9507,0xbf764d97,
0x3f800000,0x0,0x3f764d97,0xbe8b9507,0x3f59f26a,0xbf064b82,0x3f2d1469,0xbf3ca003,0x3f663375,0xbfe4aa59,0x3e419b37,0xbf7b61fc,0xbdafb680,0xbf7f0e58,0xbeb554ec,0xbf6f6830,
0x3f800000,0x0,0x3f756d97,0xbe919ddd,0x3f5695e5,0xbf0b9a6b,0x3f26050a,0xbf42de29,0x3f4f7bca,0xbfea09a7,0x3e039502,0xbf7de0b1,0xbe22abb6,0xbf7cbfc9,0xbeddbe79,0xbf66becc,
0x3f800000,0x0,0x3f748422,0xbe97a117,0x3f531849,0xbf10d3cd,0x3f1ebc12,0xbf48d8b3,0x3f38442a,0xbfeed89e,0x3d8a200a,0xbf7f6ac7,0xbe6c9a7f,0xbf791298,0xbf0242b1,0xbf5c61c7,
0x3f800000,0x0,0x3f73913f,0xbe9d9e78,0x3f4f7a1f,0xbf15f6d9,0x3f173c07,0xbf4e8d90,0x3f209ae5,0xbff31447,0x3bc90f88,0xbf7ffec4,0xbe9aa086,0xbf740bdd,0xbf14b039,0xbf5064af,
0x3f800000,0x0,0x3f7294f8,0xbea395c5,0x3f4bbbf8,0xbf1b02c6,0x3f0f8784,0xbf53fac3,0x3f088e93,0xbff6ba07,0xbd621469,0xbf7f9c18,0xbebe1d4a,0xbf6db293,0xbf26050a,0xbf42de29,
0x3f800000,0x0,0x3f718f57,0xbea986c4,0x3f47de65,0xbf1ff6cb,0x3f07a136,0xbf591e6a,0x3ee05c13,0xbff9c79d,0xbdee3876,0xbf7e4323,0xbee0924f,0xbf660f88,0xbf36206c,0xbf33e7bc,
0x3f800000,0x0,0x3f708066,0xbeaf713a,0x3f43e200,0xbf24d225,0x3eff17b2,0xbf5df6be,0x3eaf10a2,0xbffc3b28,0xbe354098,0xbf7bf531,0xbf00e7e4,0xbf5d2d53,0xbf44e3f5,0xbf239da9,
0x3f800000,0x0,0x3f6f6830,0xbeb554ec,0x3f3fc767,0xbf299415,0x3eee9479,0xbf628210,0x3e7ab273,0xbffe1324,0xbe72b651,0xbf78b47b,0xbf10d3cd,0xbf531849,0xbf5233c6,0xbf121eb0,
0x3f800000,0x0,0x3f6e46be,0xbebb31a0,0x3f3b8f3b,0xbf2e3bde,0x3eddbe79,0xbf66becc,0x3e16a905,0xbfff4e6d,0xbe97a117,0xbf748422,0xbf1ff6cb,0xbf47de65,0xbf5df6be,0xbeff17b2,
0x3f800000,0x0,0x3f6d1c1d,0xbec1071e,0x3f373a23,0xbf32c8c9,0x3ecc9b8b,0xbf6aab7b,0x3d490ab0,0xbfffec43,0xbeb554ec,0xbf6f6830,0xbf2e3bde,0xbf3b8f3b,0xbf6816a8,0xbed8106b,
0x3f800000,0x0,0x3f7ffd39,0xbc16cb58,0x3f7ff4e6,0xbc96c9b6,0x3f7fe705,0xbce22a7a,0x3fffd397,0xbd96c32c,0x3f7fba9e,0xbd3c6dd5,0x3f7f9c18,0xbd621469,0x3f7f7808,0xbd83db0a,
0x3f800000,0x0,0x3f7ff0e3,0xbcafea69,0x3f7fc38f,0xbd2fe007,0x3f7f7808,0xbd83db0a,0x3fff0e58,0xbe2fb680,0x3f7e868b,0xbddb7d37,0x3f7de0b1,0xbe039502,0x3f7d1cdd,0xbe195be0,
0x3f800000,0x0,0x3f7fdaaf,0xbd0a342f,0x3f7f6ac7,0xbd8a200a,0x3f7eb069,0xbdcefdb7,0x3ffdabcc,0xbe89cf86,0x3f7c5d3a,0xbe2bf804,0x3f7ac516,0xbe4dee60,0x3f78e3d6,0xbe6fa8b2,
0x3f800000,0x0,0x3f7fba9e,0xbd3c6dd5,0x3f7eea9d,0xbdbc3ac3,0x3f7d906e,0xbe0cec4a,0x3ffbaccd,0xbebb6ecf,0x3f7940c0,0xbe698bba,0x3f764d97,0xbe8b9507,0x3f72d4eb,0xbea21887,
0x3f800000,0x0,0x3f7f90b1,0xbd6ea038,0x3f7e4323,0xbdee3876,0x3f7c187a,0xbe3228d4,0x3ff91298,0xbeec9a7f,0x3f75341d,0xbe931f35,0x3f708066,0xbeaf713a,0x3f6afb8c,0xbecb2aae,
0x3f800000,0x0,0x3f7f5ce9,0xbd9064b4,0x3f7d7474,0xbe1008b7,0x3f7a4910,0xbe57278f,0x3ff5dec6,0xbf0e9a22,0x3f703b37,0xbeb0eacb,0x3f696591,0xbed25a09,0x3f61668a,0xbef2bd43,
0x3f800000,0x0,0x3f7f1f49,0xbda973ba,0x3f7c7eb0,0xbe28defc,0x3f7822d1,0xbe7bdba4,0x3ff21352,0xbf268f12,0x3f6a5ad9,0xbece0bea,0x3f6106f2,0xbef41f07,0x3f5627fe,0xbf0c42c9,
0x3f800000,0x0,0x3f7ed7d4,0xbdc27c39,0x3f7b61fc,0xbe419b37,0x3f75a67b,0xbe901c2c,0x3fedb293,0xbf3e1d4a,0x3f6398ac,0xbeea6681,0x3f577026,0xbf0a48ad,0x3f495521,0xbf1e1e22,
0x3f800000,0x0,0x3f7e868b,0xbddb7d37,0x3f7a1e84,0xbe5a3997,0x3f72d4eb,0xbea21887,0x3fe8bf3c,0xbf553641,0x3f5bfb34,0xbf02ef9f,0x3f4cae79,0xbf19c200,0x3f3b0629,0xbf2ecef7,
0x3f800000,0x0,0x3f7e2b72,0xbdf475c0,0x3f78b47b,0xbe72b651,0x3f6faf1b,0xbeb3dca5,0x3fe33c5a,0xbf6bcbbb,0x3f5389c7,0xbf102dd5,0x3f40d0da,0xbf286605,0x3f2b561b,0xbf3e35c5,
0x3f800000,0x0,0x3f7dc68c,0xbe06b26e,0x3f772417,0xbe8586ce,0x3f6c3624,0xbec5625c,0x3fdd2d53,0xbf80e7e4,0x3f4a4c87,0xbf1ce11f,0x3f33e7bc,0xbf36206c,0x3f1a6293,0xbf4c3578,
0x3f800000,0x0,0x3f7d57de,0xbe1324ca,0x3f756d97,0xbe919ddd,0x3f686b39,0xbed6a399,0x3fd695e5,0xbf8b9a6b,0x3f404c5c,0xbf28fd41,0x3f26050a,0xbf42de29,0x3f084b92,0xbf58b3a1,
0x3f800000,0x0,0x3f7cdf6c,0xbe1f917b,0x3f73913f,0xbe9d9e78,0x3f644fac,0xbee79a5d,0x3fcf7a1f,0xbf95f6d9,0x3f3592e7,0xbf34768f,0x3f173c07,0xbf4e8d90,0x3eea6681,0xbf6398ac,
0x3f800000,0x0,0x3f7c5d3a,0xbe2bf804,0x3f718f57,0xbea986c4,0x3f5fe4e9,0xbef840c8,0x3fc7de65,0xbf9ff6cb,0x3f2a2a80,0xbf3f41fc,0x3f07a136,0xbf591e6a,0x3ec27b55,0xbf6cd007,
0x3f800000,0x0,0x3f7bd14d,0xbe3857ec,0x3f6f6830,0xbeb554ec,0x3f5b2c79,0xbf044889,0x3fbfc767,0xbfa99415,0x3f1e1e22,0xbf495521,0x3eee9479,0xbf628210,0x3e9920fe,0xbf74484b,
0x3f800000,0x0,0x3f7b3bab,0xbe44b0b9,0x3f6d1c1d,0xbec1071e,0x3f5627fe,0xbf0c42c9,0x3fb73a23,0xbfb2c8c9,0x3f11796b,0xbf52a649,0x3ecc9b8b,0xbf6aab7b,0x3e5d4b1a,0xbf79f35e,
0x3f800000,0x0,0x3f7a9c59,0xbe5101f1,0x3f6aab7b,0xbecc9b8b,0x3f50d937,0xbf140c5f,0x3fae3bde,0xbfbb8f3b,0x3f044889,0xbf5b2c79,0x3ea986c4,0xbf718f57,0x3e06b26e,0xbf7dc68c,
0x3f800000,0x0,0x3f79f35e,0xbe5d4b1a,0x3f6816a8,0xbed8106b,0x3f4b41fa,0xbf1ba299,0x3fa4d225,0xbfc3e200,0x3eed3063,0xbf62df7b,0x3e8586ce,0xbf772417,0x3d3c6dd5,0xbf7fba9e,
0x3f800000,0x0,0x3f7940c0,0xbe698bba,0x3f655e0b,0xbee363fa,0x3f456439,0xbf2302d3,0x3f9b02c6,0xbfcbbbf8,0x3ed0eb2a,0xbf69b7e4,0x3e419b37,0xbf7b61fc,0xbd2351cb,0xbf7fcbe2,
0x3f800000,0x0,0x3f788486,0xbe75c35a,0x3f628210,0xbeee9479,0x3f3f41fc,0xbf2a2a80,0x3f90d3cd,0xbfd31849,0x3eb3dca5,0xbf6faf1b,0x3dee3876,0xbf7e4323,0xbe007745,0xbf7dfa38,
0x3f800000,0x0,0x3f77beb7,0xbe80f8c0,0x3f5f8327,0xbef9a02d,0x3f38dd65,0xbf311722,0x3f864b82,0xbfd9f26a,0x3e9620d2,0xbf74bf62,0x3d2fe007,0xbf7fc38f,0xbe57278f,0xbf7a4910,
0x3f800000,0x0,0x3f76ef5b,0xbe870ada,0x3f5c61c7,0xbf0242b1,0x3f3238aa,0xbf37c655,0x3f76e0cb,0xbfe04621,0x3e6fa8b2,0xbf78e3d6,0xbcfb49ba,0xbf7fe129,0xbe9620d2,0xbf74bf62,
0x3f800000,0x0,0x3f76167a,0xbe8d17c0,0x3f591e6a,0xbf07a136,0x3f2b561b,0xbf3e35c5,0x3f60924f,0xbfe60f88,0x3e3228d4,0xbf7c187a,0xbdd53db9,0xbf7e9bc9,0xbebf926f,0xbf6d67a1,
0x3f800000,0x0,0x3f75341d,0xbe931f35,0x3f55b993,0xbf0cead0,0x3f24381a,0xbf446337,0x3f49b953,0xbfeb4b0c,0x3de7fa9a,0xbf7e5a38,0xbe354098,0xbf7bf531,0xbee79a5d,0xbf644fac,
0x3f800000,0x0,0x3f74484b,0xbe9920fe,0x3f5233c6,0xbf121eb0,0x3f1ce11f,0xbf4a4c87,0x3f3263ef,0xbfeff573,0x3d55880e,0xbf7fa6e3,0xbe7ee6e1,0xbf77f110,0xbf06f686,0xbf5988ad,
0x3f800000,0x0,0x3f73530e,0xbe9f1cdf,0x3f4e8d90,0xbf173c07,0x3f1553b7,0xbf4fefa8,0x3f1aa086,0xbff40bdd,0xbc16cb58,0xbf7ffd39,0xbea395c5,0xbf7294f8,0xbf19210f,0xbf4d26fd,
0x3f800000,0x0,0x3f725470,0xbea5129f,0x3f4ac77f,0xbf1c420c,0x3f0d9281,0xbf554aa4,0x3f027dc0,0xbff78bc5,0xbd9064b4,0xbf7f5ce9,0xbec6d529,0xbf6be858,0xbf2a2a80,0xbf3f41fc,
0x3f800000,0x0,0x3f714c7a,0xbeab0201,0x3f46e22a,0xbf212ff9,0x3f05a02c,0xbf5a5ba0,0x3ed41501,0xbffa7302,0xbe06b26e,0xbf7dc68c,0xbee900b7,0xbf63f473,0xbf39f2ac,0xbf2ff3e6,
0x3f800000,0x0,0x3f703b37,0xbeb0eacb,0x3f42de29,0xbf26050a,0x3efafef7,0xbf5f20db,0x3ea2abb6,0xbffcbfc9,0xbe44b0b9,0xbf7b3bab,0xbf04f484,0xbf5ac450,0xbf485bca,0xbf1f599f,
0x3f800000,0x0,0x3f6f20b0,0xbeb6ccc3,0x3f3ebc1b,0xbf2ac082,0x3eea6681,0xbf6398ac,0x3e61bc2e,0xbffe70b0,0xbe80f8c0,0xbf77beb7,0xbf14b039,0xbf5064af,0xbf554aa4,0xbf0d9281,
0x3f800000,0x0,0x3f6dfcf2,0xbebca7af,0x3f3a7ca4,0xbf2f61a5,0x3ed97cb9,0xbf67c187,0x3dfb2b74,0xbfff84ab,0xbe9f1cdf,0xbf73530e,0xbf239da9,0xbf44e3f5,0xbf60a6cf,0xbef58035,
0x3f800000,0x0,0x3f6cd007,0xbec27b55,0x3f36206c,0xbf33e7bc,0x3ec8477c,0xbf6b99fb,0x3cc90e90,0xbffffb11,0xbebca7af,0xbf6dfcf2,0xbf31a81d,0xbf385216,0xbf6a5ad9,0xbece0bea,
0x3f800000,0x0,0x0,0x0,0x0,0x0,0x0,0x0,0x0,0x0,0x0,0x0,0x0,0x0,0x0,0x0,
0x0,0x0,0x0,0x0,0x0,0x0,0x0,0x0,0x0,0x0,0x0,0x0,0x0,0x0,0x0,0x0,
0x0,0x0,0x3e000000,0xbf20dff7,0x3ed0c429,0x0,0x3e000000,0x3e61f78b,0x3e0a8bd4,0x0,0x3e000000,0x3d5413cd,0x3d5df9ad,0x0,0x3e000000,0x3cf043ab,
0x0,0x0,0x3e000000,0x3ccbafaf,0xbd5df9ad,0x0,0x3e000000,0x3cf043ab,0xbe0a8bd4,0x0,0x3e000000,0x3d5413cd,0xbed0c429,0x0,0x3e000000,0x3e61f78b,
0x0,0x0,0x0,0x0,0x3f000000,0x0,0x0,0x3f000000,0x0,0x0,0x0,0x0,0x0,0x0,0x0,0x0,
0x0,0x0,0x0,0x0,0x0,0x0,0x0,0x0,0x0,0x0,0x0,0x0,0x3f000000,0x0,0x0,0xbf000000,
0x0,0x0,0x3e000000,0xbe3f90c7,0xbe8b7e3f,0x0,0x3e000000,0xbeb641af,0x3ea73d75,0x0,0x3e000000,0x3e9a827a,0x3da61ad1,0x0,0x3e000000,0x3dd906bd,
0x0,0x0,0x3e000000,0x3dab0dc1,0xbda61ad1,0x0,0x3e000000,0x3dd906bd,0xbea73d75,0x0,0x3e000000,0x3e9a827a,0x3e8b7e3f,0x0,0x3e000000,0xbeb641af,
0x0,0x0,0x0,0x0,0x0,0x0,0x0,0x0,0x3f000000,0x0,0x0,0x3f000000,0x0,0x0,0x0,0x0,
0x0,0x0,0x0,0x0,0x0,0x0,0x0,0x0,0x3f000000,0x0,0x0,0xbf000000,0x0,0x0,0x0,0x0,
0x0,0x0,0x3e000000,0xbdab0dc1,0xbda61ad1,0x0,0x3e000000,0xbdd906bd,0xbea73d75,0x0,0x3e000000,0xbe9a827a,0x3e8b7e3f,0x0,0x3e000000,0x3eb641af,
0x0,0x0,0x3e000000,0x3e3f90c7,0xbe8b7e3f,0x0,0x3e000000,0x3eb641af,0x3ea73d75,0x0,0x3e000000,0xbe9a827a,0x3da61ad1,0x0,0x3e000000,0xbdd906bd,
0x0,0x0,0x0,0x0,0x0,0x0,0x0,0x0,0x0,0x0,0x0,0x0,0x3f000000,0x0,0x0,0x3f000000,
0x0,0x0,0x0,0x0,0x3f000000,0x0,0x0,0xbf000000,0x0,0x0,0x0,0x0,0x0,0x0,0x0,0x0,
0x0,0x0,0x3e000000,0xbccbafaf,0xbd5df9ad,0x0,0x3e000000,0xbcf043ab,0xbe0a8bd4,0x0,0x3e000000,0xbd5413cd,0xbed0c429,0x0,0x3e000000,0xbe61f78b,
0x0,0x0,0x3e000000,0x3f20dff7,0x3ed0c429,0x0,0x3e000000,0xbe61f78b,0x3e0a8bd4,0x0,0x3e000000,0xbd5413cd,0x3d5df9ad,0x0,0x3e000000,0xbcf043ab,
};

struct Params {
    const __nv_bfloat16 *wr, *wi, *lre, *lim, *ldt, *dsk;
    float* out;
};

struct cf { float x, y; };
#define YIELD() asm volatile("pmevent 1;")
#define YS 14
#define YIELD_S1() do { if (YS & 1) YIELD(); } while (0)
#define YIELD_S2() do { if (YS & 2) YIELD(); } while (0)
#define YIELD_S3() do { if (YS & 4) YIELD(); } while (0)
__device__ __forceinline__ uint32_t smem_u32(const void* p) { return (uint32_t)__cvta_generic_to_shared(p); }
__device__ __forceinline__ void mbar_init(uint32_t a, uint32_t c) { asm volatile("mbarrier.init.shared::cta.b64 [%0], %1;" ::"r"(a), "r"(c) : "memory"); }
__device__ __forceinline__ void mbar_expect_tx(uint32_t a, uint32_t b) { asm volatile("mbarrier.arrive.expect_tx.shared::cta.b64 _, [%0], %1;" ::"r"(a), "r"(b) : "memory"); }
__device__ __forceinline__ void mbar_arrive(uint32_t a) { asm volatile("mbarrier.arrive.shared::cta.b64 _, [%0];" ::"r"(a) : "memory"); }
__device__ __forceinline__ void warp_arrive(uint32_t a) {
    __syncwarp();
    asm volatile("{.reg .pred p; elect.sync _|p, 0xffffffff; @p mbarrier.arrive.shared::cta.b64 _, [%0];}" ::"r"(a) : "memory");
}
__device__ __forceinline__ uint32_t mbar_try(uint32_t a, uint32_t ph) {
    uint32_t ok;
    asm volatile("{.reg .pred p; mbarrier.try_wait.parity.shared::cta.b64 p, [%1], %2; selp.u32 %0, 1, 0, p;}" : "=r"(ok) : "r"(a), "r"(ph) : "memory");
    return ok;
}
__device__ __forceinline__ void mbar_wait(uint32_t a, uint32_t ph) {
    uint32_t ok, n = 0;
    do { ok = mbar_try(a, ph); } while (!ok && ++n < SPIN_LIMIT);
}
__device__ __forceinline__ void mbar_wait_fast(uint32_t a, uint32_t ph) { if (!mbar_try(a, ph)) mbar_wait(a, ph); }
__device__ __forceinline__ unsigned ld_rlx(const unsigned* p) { unsigned v; asm volatile("ld.relaxed.gpu.global.u32 %0, [%1];" : "=r"(v) : "l"(p) : "memory"); return v; }
__device__ __forceinline__ void wait_cnt(const unsigned* p, unsigned target) {
    unsigned n = 0;
    while ((int)(ld_rlx(p) - target) < 0 && ++n < SPIN_LIMIT) __nanosleep(20);
}
__device__ __forceinline__ void red_hint(unsigned* p) { asm volatile("red.relaxed.gpu.global.add.u32 [%0], 1;" ::"l"(p) : "memory"); }
__device__ __forceinline__ void fence_async_sm() { asm volatile("fence.proxy.async.shared::cta;" ::: "memory"); }
#define bar_sync(id, n) asm volatile("bar.sync %0, %1;" ::"n"(id), "n"(n) : "memory")
#define bar_arrive(id, n) asm volatile("bar.arrive %0, %1;" ::"n"(id), "n"(n) : "memory")
__device__ __forceinline__ bool elect_one() {
    uint32_t r;
    asm volatile("{.reg .pred p; elect.sync _|p, 0xffffffff; selp.u32 %0, 1, 0, p;}" : "=r"(r));
    return r != 0;
}

__device__ __forceinline__ void tma2d(uint32_t dst, const CUtensorMap* m, int c0, int c1, uint32_t bar) {
    asm volatile("cp.async.bulk.tensor.2d.shared::cluster.global.mbarrier::complete_tx::bytes [%0], [%1, {%3,%4}], [%2];" ::"r"(dst), "l"(m), "r"(bar), "r"(c0), "r"(c1) : "memory");
}
__device__ __forceinline__ void tma3d(uint32_t dst, const CUtensorMap* m, int c0, int c1, int c2, uint32_t bar) {
    asm volatile("cp.async.bulk.tensor.3d.shared::cluster.global.mbarrier::complete_tx::bytes [%0], [%1, {%3,%4,%5}], [%2];" ::"r"(dst), "l"(m), "r"(bar), "r"(c0), "r"(c1), "r"(c2) : "memory");
}
__device__ __forceinline__ void tma4d_mc(uint32_t dst, const CUtensorMap* m, int c0, int c1, int c2, int c3, uint32_t bar) {
    asm volatile("cp.async.bulk.tensor.4d.shared::cluster.global.mbarrier::complete_tx::bytes.multicast::cluster [%0], [%1, {%3,%4,%5,%6}], [%2], %7;" ::"r"(dst), "l"(m), "r"(bar), "r"(c0), "r"(c1), "r"(c2), "r"(c3), "h"((uint16_t)3) : "memory");
}
__device__ __forceinline__ void tma4d(uint32_t dst, const CUtensorMap* m, int c0, int c1, int c2, int c3, uint32_t bar) {
    asm volatile("cp.async.bulk.tensor.4d.shared::cluster.global.mbarrier::complete_tx::bytes [%0], [%1, {%3,%4,%5,%6}], [%2];" ::"r"(dst), "l"(m), "r"(bar), "r"(c0), "r"(c1), "r"(c2), "r"(c3) : "memory");
}
__device__ __forceinline__ void tma2d_st(const CUtensorMap* m, int c0, int c1, uint32_t src) {
    asm volatile("cp.async.bulk.tensor.2d.global.shared::cta.bulk_group [%0, {%2,%3}], [%1];" ::"l"(m), "r"(src), "r"(c0), "r"(c1) : "memory");
}
__device__ __forceinline__ void tma5d(uint32_t dst, const CUtensorMap* m, int c0, int c1, int c2, int c3, int c4, uint32_t bar) {
    asm volatile("cp.async.bulk.tensor.5d.shared::cluster.global.mbarrier::complete_tx::bytes [%0], [%1, {%3,%4,%5,%6,%7}], [%2];" ::"r"(dst), "l"(m), "r"(bar), "r"(c0), "r"(c1), "r"(c2), "r"(c3), "r"(c4) : "memory");
}
__device__ __forceinline__ void bulk_ld(uint32_t dst, const void* src, uint32_t n, uint32_t bar) {
    asm volatile("cp.async.bulk.shared::cluster.global.mbarrier::complete_tx::bytes [%0], [%1], %2, [%3];" ::"r"(dst), "l"(src), "r"(n), "r"(bar) : "memory");
}
__device__ __forceinline__ void bulk_st(void* dst, uint32_t src, uint32_t n) {
    asm volatile("cp.async.bulk.global.shared::cta.bulk_group [%0], [%1], %2;" ::"l"(dst), "r"(src), "r"(n) : "memory");
}
__device__ __forceinline__ void bulk_commit() { asm volatile("cp.async.bulk.commit_group;" ::: "memory"); }
__device__ __forceinline__ void bulk_wait_read() { asm volatile("cp.async.bulk.wait_group.read 0;" ::: "memory"); }
__device__ __forceinline__ void bulk_wait_all() { asm volatile("cp.async.bulk.wait_group 0;" ::: "memory"); }
__device__ __forceinline__ void stsm4(uint32_t a, uint32_t r0, uint32_t r1, uint32_t r2, uint32_t r3) {
    asm volatile("stmatrix.sync.aligned.m8n8.x4.shared.b16 [%0], {%1,%2,%3,%4};" ::"r"(a), "r"(r0), "r"(r1), "r"(r2), "r"(r3) : "memory");
}
__device__ __forceinline__ void sts128(uint32_t a, uint32_t r0, uint32_t r1, uint32_t r2, uint32_t r3) {
    asm volatile("st.shared.v4.b32 [%0], {%1,%2,%3,%4};" ::"r"(a), "r"(r0), "r"(r1), "r"(r2), "r"(r3) : "memory");
}
__device__ __forceinline__ void lds128f(uint32_t a, float& x, float& y, float& z, float& u) { asm volatile("ld.shared.v4.f32 {%0,%1,%2,%3}, [%4];" : "=f"(x), "=f"(y), "=f"(z), "=f"(u) : "r"(a) : "memory"); }
__device__ __forceinline__ cf lds_cf(uint32_t a) { cf v; asm volatile("ld.shared.v2.f32 {%0,%1}, [%2];" : "=f"(v.x), "=f"(v.y) : "r"(a) : "memory"); return v; }
__device__ __forceinline__ void stg128(const void* a, uint32_t r0, uint32_t r1, uint32_t r2, uint32_t r3) {
    asm volatile("st.global.v4.b32 [%0], {%1,%2,%3,%4};" ::"l"(a), "r"(r0), "r"(r1), "r"(r2), "r"(r3) : "memory");
}
__device__ __forceinline__ int fresh_lane() { int v; asm volatile("mov.u32 %0, %%laneid;" : "=r"(v)); return v; }
__device__ __forceinline__ uint32_t opaque32(uint32_t v) { asm volatile("" : "+r"(v)); return v; }
__device__ __forceinline__ const uint8_t* padd(const void* base, uint32_t off) {
    uint64_t r;
    asm("{.reg .u32 l, h; mov.b64 {l, h}, %1; add.cc.u32 l, l, %2; addc.u32 h, h, 0; mov.b64 %0, {l, h};}" : "=l"(r) : "l"(base), "r"(off));
    return (const uint8_t*)r;
}
template <int N, int STRIDE> __device__ __forceinline__ void ldtab(uint32_t (&v)[4 * N], uint32_t off) {
    const uint8_t* a = padd(g_tab, off);
#pragma unroll
    for (int i = 0; i < N; i++)
        asm volatile("ld.global.nc.v4.b32 {%0,%1,%2,%3}, [%4];" : "=r"(v[4 * i]), "=r"(v[4 * i + 1]), "=r"(v[4 * i + 2]), "=r"(v[4 * i + 3]) : "l"(a + i * STRIDE));
}
template <int STRIDE> __device__ __forceinline__ void ldtab_cf(cf (&t)[8], uint32_t off) {
    uint32_t v[16];
    ldtab<4, STRIDE>(v, off);
#pragma unroll
    for (int i = 0; i < 8; i++) t[i] = {__uint_as_float(v[2 * i]), __uint_as_float(v[2 * i + 1])};
}
__device__ __forceinline__ uint32_t lds16(uint32_t a) { uint32_t v; asm volatile("ld.shared.u16 %0, [%1];" : "=r"(v) : "r"(a)); return v; }
__device__ __forceinline__ unsigned get_epoch(uint32_t bars) {
    mbar_wait(bars + B_EP, 0);
    unsigned e;
    asm volatile("ld.shared.u32 %0, [%1];" : "=r"(e) : "r"(bars + B_EPOCH) : "memory");
    return e;
}
__device__ __forceinline__ void sts64(uint32_t a, uint32_t x, uint32_t y) { asm volatile("st.shared.v2.b32 [%0], {%1,%2};" ::"r"(a), "r"(x), "r"(y) : "memory"); }
__device__ __forceinline__ uint32_t pk(float lo, float hi) { uint32_t r; asm("cvt.rn.bf16x2.f32 %0, %1, %2;" : "=r"(r) : "f"(hi), "f"(lo)); return r; }
__device__ __forceinline__ float bf2f(unsigned short v) { return __uint_as_float((uint32_t)v << 16); }

__device__ __forceinline__ uint64_t mkdesc(uint32_t addr, uint32_t lbo, uint32_t sbo, uint32_t swz) {
    return (uint64_t)((addr & 0x3FFFF) >> 4) | ((uint64_t)(lbo >> 4) << 16) | ((uint64_t)(sbo >> 4) << 32) | ((uint64_t)swz << 62);
}
__device__ __forceinline__ uint64_t opaque(uint64_t v) { asm volatile("" : "+l"(v)); return v; }
__device__ __forceinline__ void wg_fence() { asm volatile("wgmma.fence.sync.aligned;" ::: "memory"); }
__device__ __forceinline__ void wg_commit() { asm volatile("wgmma.commit_group.sync.aligned;" ::: "memory"); }
template <int N> __device__ __forceinline__ void wg_wait() { asm volatile("wgmma.wait_group.sync.aligned %0;" ::"n"(N) : "memory"); }
template <int N> __device__ __forceinline__ void pin(float (&d)[N]) {
#pragma unroll
    for (int i = 0; i < N; i++) asm volatile("" : "+f"(d[i])::"memory");
}
template <int N> __device__ __forceinline__ void pinu(uint32_t (&d)[N]) {
#pragma unroll
    for (int i = 0; i < N; i++) asm volatile("" : "+r"(d[i])::"memory");
}

#define R8(d, o) "+f"(d[o]), "+f"(d[o + 1]), "+f"(d[o + 2]), "+f"(d[o + 3]), "+f"(d[o + 4]), "+f"(d[o + 5]), "+f"(d[o + 6]), "+f"(d[o + 7])
#define L8 "%0,%1,%2,%3,%4,%5,%6,%7"
#define L32 L8 ",%8,%9,%10,%11,%12,%13,%14,%15,%16,%17,%18,%19,%20,%21,%22,%23,%24,%25,%26,%27,%28,%29,%30,%31"
#define L56 L32 ",%32,%33,%34,%35,%36,%37,%38,%39,%40,%41,%42,%43,%44,%45,%46,%47,%48,%49,%50,%51,%52,%53,%54,%55"
#define L64 L56 ",%56,%57,%58,%59,%60,%61,%62,%63"

template <int O, int TA, int TB, int N> __device__ __forceinline__ void mma128_ss(float (&d)[N], uint64_t da, uint64_t db, int sc) {
    asm volatile("{.reg .pred p; setp.ne.b32 p, %66, 0;\n"
                 "wgmma.mma_async.sync.aligned.m64n128k16.f32.bf16.bf16 {" L64 "}, %64, %65, p, 1, 1, %67, %68;}"
                 : R8(d, O), R8(d, O + 8), R8(d, O + 16), R8(d, O + 24), R8(d, O + 32), R8(d, O + 40), R8(d, O + 48), R8(d, O + 56)
                 : "l"(da), "l"(db), "r"(sc), "n"(TA), "n"(TB));
}
template <int O, int TB> __device__ __forceinline__ void mma128_rs(float (&d)[128], uint32_t a0, uint32_t a1, uint32_t a2, uint32_t a3, uint64_t db, int sc) {
    asm volatile("{.reg .pred p; setp.ne.b32 p, %69, 0;\n"
                 "wgmma.mma_async.sync.aligned.m64n128k16.f32.bf16.bf16 {" L64 "}, {%64,%65,%66,%67}, %68, p, 1, 1, %70;}"
                 : R8(d, O), R8(d, O + 8), R8(d, O + 16), R8(d, O + 24), R8(d, O + 32), R8(d, O + 40), R8(d, O + 48), R8(d, O + 56)
                 : "r"(a0), "r"(a1), "r"(a2), "r"(a3), "l"(db), "r"(sc), "n"(TB));
}
template <int TB> __device__ __forceinline__ void mma64_rs(float (&d)[32], uint32_t a0, uint32_t a1, uint32_t a2, uint32_t a3, uint64_t db, int sc) {
    asm volatile("{.reg .pred p; setp.ne.b32 p, %37, 0;\n"
                 "wgmma.mma_async.sync.aligned.m64n64k16.f32.bf16.bf16 {" L32 "}, {%32,%33,%34,%35}, %36, p, 1, 1, %38;}"
                 : R8(d, 0), R8(d, 8), R8(d, 16), R8(d, 24)
                 : "r"(a0), "r"(a1), "r"(a2), "r"(a3), "l"(db), "r"(sc), "n"(TB));
}
__device__ __forceinline__ void mma112_ss(float (&d)[64], uint64_t da, uint64_t db, int sc) {
    asm volatile("{.reg .pred p; setp.ne.b32 p, %58, 0;\n"
                 "wgmma.mma_async.sync.aligned.m64n112k16.f32.bf16.bf16 {" L56 "}, %56, %57, p, 1, 1, 0, 1;}"
                 : R8(d, 8), R8(d, 16), R8(d, 24), R8(d, 32), R8(d, 40), R8(d, 48), R8(d, 56)
                 : "l"(da), "l"(db), "r"(sc));
}
__device__ __forceinline__ void mma16_rs(float (&d)[64], uint32_t a0, uint32_t a1, uint32_t a2, uint32_t a3, uint64_t db, int sc) {
    asm volatile("{.reg .pred p; setp.ne.b32 p, %13, 0;\n"
                 "wgmma.mma_async.sync.aligned.m64n16k16.f32.bf16.bf16 {" L8 "}, {%8,%9,%10,%11}, %12, p, 1, 1, 1;}"
                 : R8(d, 0)
                 : "r"(a0), "r"(a1), "r"(a2), "r"(a3), "l"(db), "r"(sc));
}

__device__ __forceinline__ cf cmul(cf a, cf b) { return {fmaf(a.x, b.x, -a.y * b.y), fmaf(a.x, b.y, a.y * b.x)}; }
__device__ __forceinline__ cf cmulc(cf a, cf b) { return {fmaf(a.x, b.x, a.y * b.y), fmaf(a.y, b.x, -a.x * b.y)}; }
__device__ __forceinline__ cf cfma(cf a, cf b, cf c) { return {fmaf(a.x, b.x, fmaf(-a.y, b.y, c.x)), fmaf(a.x, b.y, fmaf(a.y, b.x, c.y))}; }
__device__ __forceinline__ cf csq(cf a) { return {fmaf(a.x, a.x, -a.y * a.y), (a.x * a.y) * 2.f}; }
__device__ __forceinline__ cf csel(int c, cf a, cf b) {
    cf r;
    asm("{.reg .pred p; setp.ne.s32 p, %2, 0; selp.f32 %0, %3, %5, p; selp.f32 %1, %4, %6, p;}" : "=f"(r.x), "=f"(r.y) : "r"(c), "f"(a.x), "f"(a.y), "f"(b.x), "f"(b.y));
    return r;
}
__device__ __forceinline__ cf cadd(cf a, cf b) { return {a.x + b.x, a.y + b.y}; }
__device__ __forceinline__ cf csub(cf a, cf b) { return {a.x - b.x, a.y - b.y}; }
__device__ __forceinline__ cf twice_minus(cf a, cf s) { return {fmaf(2.f, a.x, -s.x), fmaf(2.f, a.y, -s.y)}; }
__device__ __forceinline__ cf twid(int m, int M) {
    int r = ((m + M / 2) & (M - 1)) - M / 2;
    float s, c;
    __sincosf((float)r * (-6.283185307179586f / (float)M), &s, &c);
    return {c, s};
}
struct c2 { cf a, b; };
#define YP1 3
#define YP2 0
#define YP3 3
template <int Y> __device__ __forceinline__ void fin(c2& u) { if (Y & 1) asm volatile("pmevent 1;" : "+f"(u.a.x), "+f"(u.a.y), "+f"(u.b.x), "+f"(u.b.y)); }
template <int Y> __device__ __forceinline__ void fin(c2& u, c2& v) {
    if (Y & 2) asm volatile("pmevent 1;" : "+f"(u.a.x), "+f"(u.a.y), "+f"(u.b.x), "+f"(u.b.y), "+f"(v.a.x), "+f"(v.a.y), "+f"(v.b.x), "+f"(v.b.y));
}
__device__ __forceinline__ c2 mul2(c2 u, cf t) { return {cmul(u.a, t), cmul(u.b, t)}; }
__device__ __forceinline__ c2 mul2(c2 u, c2 t) { return {cmul(u.a, t.a), cmul(u.b, t.b)}; }
__device__ __forceinline__ c2 fma2(c2 u, cf t, c2 c) { return {cfma(u.a, t, c.a), cfma(u.b, t, c.b)}; }
__device__ __forceinline__ c2 fma2(c2 u, c2 t, c2 c) { return {cfma(u.a, t.a, c.a), cfma(u.b, t.b, c.b)}; }
__device__ __forceinline__ c2 twm2(c2 u, c2 s) { return {twice_minus(u.a, s.a), twice_minus(u.b, s.b)}; }
template <int Y> __device__ __forceinline__ void bfly(c2& u, c2& v) { const c2 t = u; u = {cadd(t.a, v.a), cadd(t.b, v.b)}; v = {csub(t.a, v.a), csub(t.b, v.b)}; fin<Y>(u, v); }
template <int Y> __device__ __forceinline__ void bfly_mi(c2& u, c2& v) {
    const c2 t = u, z = v;
    u = {{t.a.x + z.a.y, t.a.y - z.a.x}, {t.b.x + z.b.y, t.b.y - z.b.x}};
    v = {{t.a.x - z.a.y, t.a.y + z.a.x}, {t.b.x - z.b.y, t.b.y + z.b.x}};
    fin<Y>(u, v);
}
template <int Y> __device__ __forceinline__ void bfly_s(c2& u, c2& v) {
    const float s = 0.70710678118654752f;
    const c2 t = u, z = v;
    u = {{fmaf(s, z.a.x, t.a.x), fmaf(s, z.a.y, t.a.y)}, {fmaf(s, z.b.x, t.b.x), fmaf(s, z.b.y, t.b.y)}};
    v = {{fmaf(-s, z.a.x, t.a.x), fmaf(-s, z.a.y, t.a.y)}, {fmaf(-s, z.b.x, t.b.x), fmaf(-s, z.b.y, t.b.y)}};
    fin<Y>(u, v);
}
template <int Y, class T> __device__ __forceinline__ void bfly_tw(c2& u0, c2& v0, T t0, c2& u1, c2& v1, T t1) {
    v0 = fma2(v0, t0, u0); fin<Y>(v0);
    v1 = fma2(v1, t1, u1); fin<Y>(v1);
    const c2 a = twm2(u0, v0), b = twm2(u1, v1);
    u0 = v0; u1 = v1; v0 = a; v1 = b;
    fin<Y>(v0, v1);
}
template <bool TW, int Y> __device__ __forceinline__ void dft8(c2 (&v)[8], const cf (&tw)[8]) {
    if (TW) {
#pragma unroll
        for (int n = 1; n < 4; n++) { v[n] = mul2(v[n], tw[n]); fin<Y>(v[n]); }
        bfly_tw<Y>(v[0], v[4], tw[4], v[2], v[6], tw[6]);
        bfly_tw<Y>(v[1], v[5], tw[5], v[3], v[7], tw[7]);
    } else {
#pragma unroll
        for (int n = 0; n < 4; n++) bfly<Y>(v[n], v[n + 4]);
    }
    bfly<Y>(v[0], v[2]); bfly_mi<Y>(v[4], v[6]);
    bfly<Y>(v[1], v[3]); bfly_mi<Y>(v[5], v[7]);
    v[5] = {{v[5].a.x + v[5].a.y, v[5].a.y - v[5].a.x}, {v[5].b.x + v[5].b.y, v[5].b.y - v[5].b.x}};
    v[7] = {{v[7].a.y - v[7].a.x, -v[7].a.x - v[7].a.y}, {v[7].b.y - v[7].b.x, -v[7].b.x - v[7].b.y}};
    fin<Y>(v[5], v[7]);
    bfly<Y>(v[0], v[1]); bfly_s<Y>(v[4], v[5]); bfly_mi<Y>(v[2], v[3]); bfly_s<Y>(v[6], v[7]);
    const c2 t1 = v[1], t3 = v[3];
    v[1] = v[4]; v[4] = t1; v[3] = v[6]; v[6] = t3;
}

__device__ __forceinline__ void gather(uint64_t (&fv)[4], const uint8_t* a, int n) {
    asm volatile("{.reg .pred p0, p1, p2, p3;\n"
                 "setp.ge.s32 p0, %5, 0; setp.ge.s32 p1, %5, 4; setp.ge.s32 p2, %5, 8; setp.ge.s32 p3, %5, 12;\n"
                 "@p0 ld.relaxed.gpu.global.b64 %0, [%4]; @p1 ld.relaxed.gpu.global.b64 %1, [%4+-32768];\n"
                 "@p2 ld.relaxed.gpu.global.b64 %2, [%4+-65536]; @p3 ld.relaxed.gpu.global.b64 %3, [%4+-98304];}"
                 : "+l"(fv[0]), "+l"(fv[1]), "+l"(fv[2]), "+l"(fv[3]) : "l"(a), "r"(n) : "memory");
}
__device__ __forceinline__ cf as_cf(uint64_t v) { cf r; asm("mov.b64 {%0,%1}, %2;" : "=f"(r.x), "=f"(r.y) : "l"(v)); return r; }
template <int H> __device__ __forceinline__ void prescale(float (&u)[64], const float (&d)[128], cf gam) {
#pragma unroll
    for (int i = 0; i < 32; i += 2) {
        const int r = 2 * i + 2 * H;
        c2 v = mul2(c2{{d[r], -d[64 + r]}, {d[r + 1], -d[65 + r]}}, gam);
        if (YS & 2) asm volatile("pmevent 1;" : "+f"(v.a.x), "+f"(v.a.y), "+f"(v.b.x), "+f"(v.b.y));
        u[i] = v.a.x; u[32 + i] = v.a.y; u[i + 1] = v.b.x; u[33 + i] = v.b.y;
    }
}
__device__ __forceinline__ void scan2(const float (&u)[64], cf lam, cf st, const uint8_t* hptr, uint32_t hm, uint32_t hb, uint32_t& keep) {
    uint32_t hp[32];
#pragma unroll
    for (int jj = 0; jj < 4; jj++) {
        cf v[8];
#pragma unroll
        for (int i = 0; i < 8; i++) v[i] = st = cfma(lam, st, {u[8 * jj + i], u[32 + 8 * jj + i]});
        const int o = 8 * jj;
        hp[o] = pk(v[0].x, v[2].x); hp[o + 1] = pk(v[4].x, v[6].x); hp[o + 2] = pk(v[1].x, v[3].x); hp[o + 3] = pk(v[5].x, v[7].x);
        hp[o + 4] = pk(v[0].y, v[2].y); hp[o + 5] = pk(v[4].y, v[6].y); hp[o + 6] = pk(v[1].y, v[3].y); hp[o + 7] = pk(v[5].y, v[7].y);
        hp[o + jj] = (hp[o + jj] & hm) | hb;
        hp[o + 4 + jj] = (hp[o + 4 + jj] & hm) | hb;
        stg128(hptr + (jj >> 1) * 8192 + (jj & 1) * 512, hp[o], hp[o + 1], hp[o + 2], hp[o + 3]);
        stg128(hptr + 16384 + (jj >> 1) * 8192 + (jj & 1) * 512, hp[o + 4], hp[o + 5], hp[o + 6], hp[o + 7]);
        YIELD_S3();
        if (jj > 0) {
#pragma unroll
            for (int i = o - 8; i < o; i += 2) asm volatile("lop3.b32 %0, %0, %1, %2, 0x80;" : "+r"(keep) : "r"(hp[i]), "r"(hp[i + 1]));
        }
    }
}

__device__ __forceinline__ int pos_of(int n) { return (n & 24) + 4 * (n & 1) + ((n >> 1) & 3); }
__device__ __forceinline__ int unit_of(int role, int u, int& slot) {
    const int g = role & 7, w = (role >> 3) & 3, b = role >> 5;
    slot = role >= 128 ? g : (g ? 16 * g + w + 4 * b : 4 * w + b);
    return role >= 128 ? 32 * max(2 * g + u, 1) : (g ? g + 16 * w : ((w & 1) << 4) + ((w & 2) << 2)) + 64 * b + 256 * u;
}
template <int STRIDE> __device__ __forceinline__ bool tags_ok(uint32_t a, uint32_t ep) {
    uint32_t v[4], ok;
#pragma unroll
    for (int i = 0; i < 4; i++) asm volatile("ld.shared.u32 %0, [%1];" : "=r"(v[i]) : "r"(a + i * STRIDE) : "memory");
    asm volatile("{.reg .pred p; .reg .b32 a, b; lop3.b32 a, %1, %2, %5, 0x7e; lop3.b32 b, %3, %4, %5, 0x7e; lop3.b32 a, a, b, 1, 0xa8;\n"
                 "setp.eq.u32 p, a, 0; vote.sync.all.pred p, p, -1; selp.u32 %0, 1, 0, p;}" : "=r"(ok) : "r"(v[0]), "r"(v[1]), "r"(v[2]), "r"(v[3]), "r"(ep));
    return ok;
}
__device__ __forceinline__ void load_w_rows(uint32_t dst, const CUtensorMap* mr, const CUtensorMap* mi, int kap, uint32_t bar) {
    mbar_expect_tx(bar, 16 * WPITCH);
#pragma unroll 1
    for (int i = 0; i < 2; i++, dst += 8 * WPITCH, kap = (512 - kap) & 511) {
        tma2d(dst, mr, (kap * 1026 >> 4) * 2, 0, bar);
        tma2d(dst + 4 * WPITCH, mi, (kap * 1026 >> 4) * 2, 0, bar);
    }
}
__device__ __forceinline__ void prefetch_w_rows(const CUtensorMap* mr, const CUtensorMap* mi, int kap) {
#pragma unroll 1
    for (int i = 0; i < 2; i++, kap = (512 - kap) & 511) {
        asm volatile("cp.async.bulk.prefetch.tensor.2d.L2.global [%0, {%1,%2}];" ::"l"(mr), "r"((kap * 1026 >> 4) * 2), "r"(0) : "memory");
        asm volatile("cp.async.bulk.prefetch.tensor.2d.L2.global [%0, {%1,%2}];" ::"l"(mi), "r"((kap * 1026 >> 4) * 2), "r"(0) : "memory");
    }
}
template <int K0, int K1> __device__ __forceinline__ void store_v(const uint32_t (&vo)[32], const uint8_t* vp, bool p) {
    if (p) {
#pragma unroll
        for (int k = K0; k < K1; k++)
            asm volatile("st.global.v2.b32 [%0], {%1,%2};" ::"l"(vp + (k >> 2) * (1 << 20) + ((k >> 1) & 1) * 8192 + (k & 1) * (4 * 32768)), "r"(vo[2 * k]), "r"(vo[2 * k + 1]) : "memory");
    }
}
#define SB0 1024
__device__ __forceinline__ uint64_t ring_desc(uint32_t sb, uint32_t off, uint32_t lbo, uint32_t swz) {
    uint64_t d;
    asm volatile("{.reg .b32 z; shr.u32 z, %1, 28; mov.b64 %0, {z, z}; add.u64 %0, %0, %2;}" : "=l"(d) : "r"(sb), "l"(mkdesc(SB0 + off, lbo, 1024, swz)));
    return d;
}
struct Ring {
    uint32_t full, rel;
    uint32_t n;
    bool sig;
};
__device__ __forceinline__ void ring_release(const Ring& r, uint32_t o) {
    if (r.sig) asm volatile("mbarrier.arrive.shared::cluster.b64 _, [%0];" ::"r"(r.rel + o) : "memory");
}
__device__ __forceinline__ void peek(uint32_t a, uint32_t ph) { asm volatile("mbarrier.test_wait.parity.shared::cta.b64 pk, [%0], %1;" ::"r"(a), "r"(ph) : "memory"); }
__device__ __forceinline__ void peek_wait(uint32_t a, uint32_t ph, uint32_t& n) {
    asm volatile("{@pk bra DONE;\n"
                 "LOOP: mbarrier.try_wait.parity.shared::cta.b64 pk, [%1], %2; add.u32 %0, %0, 1; setp.gt.or.u32 pk, %0, %3, pk; @!pk bra LOOP;\n"
                 "DONE: }" : "+r"(n) : "r"(a), "r"(ph), "n"(SPIN_LIMIT) : "memory");
}
#define SL(k) ((k) % NST)
#define PH(k) (((k) / NST) & 1)
#define H64 "%64,%65,%66,%67,%68,%69,%70,%71,%72,%73,%74,%75,%76,%77,%78,%79,%80,%81,%82,%83,%84,%85,%86,%87,%88,%89,%90,%91,%92,%93,%94,%95," \
            "%96,%97,%98,%99,%100,%101,%102,%103,%104,%105,%106,%107,%108,%109,%110,%111,%112,%113,%114,%115,%116,%117,%118,%119,%120,%121,%122,%123,%124,%125,%126,%127"
#define WG_MMA "wgmma.mma_async.sync.aligned.m64n128k16.f32.bf16.bf16 "
#define DESC_B(S, j) "mov.b64 {t, hb}, %130; mov.b64 db, {%137 + 2048 * " #S " + 2 * " #j ", hb};\n"
#define MMA_LO(S, j, p) "add.u64 da, %129, 2048 * " #S " + %136 * " #j ";" DESC_B(S, j) WG_MMA "{" L64 "}, da, db, " #p ", 1, 1, %138, 0;\n"
#define MMA_HI(S, j, p) "add.u64 da, %129, 2048 * " #S " + 512 + %136 * " #j ";\n" WG_MMA "{" H64 "}, da, db, " #p ", 1, 1, %138, 0;\n"
#define STEP(S, P, N, ph, pa, pr, X, Y) \
    "wgmma.fence.sync.aligned;\n" MMA_LO(S, 0, pa) MMA_HI(S, 0, pa) \
    "wgmma.commit_group.sync.aligned; wgmma.wait_group.sync.aligned 1; @" #pr " mbarrier.arrive.shared::cluster.b64 _, [%132 + 8 * " #P "];\n" MMA_LO(S, 1, 1) \
    "mbarrier.test_wait.parity.shared::cta.b64 pk, [%131 + 8 * " #N "], " #ph ";\n" MMA_HI(S, 1, 1) MMA_LO(S, 2, 1) X MMA_HI(S, 2, 1) MMA_LO(S, 3, 1) MMA_HI(S, 3, 1) \
    "wgmma.commit_group.sync.aligned;\n" P4A Y "@pk bra GO" #S ";\n" \
    "WAIT" #S ": mbarrier.try_wait.parity.shared::cta.b64 pk, [%131 + 8 * " #N "], " #ph "; add.u32 %128, %128, 1; setp.gt.or.u32 pk, %128, %139, pk; @!pk bra WAIT" #S ";\n" \
    "GO" #S ":\n" P4B
#define P4A
#define P4B
#define P4I
#define P4O
#define STEP_ARGS(TA) \
    : R8(d, 0), R8(d, 8), R8(d, 16), R8(d, 24), R8(d, 32), R8(d, 40), R8(d, 48), R8(d, 56), \
      R8(d, 64), R8(d, 72), R8(d, 80), R8(d, 88), R8(d, 96), R8(d, 104), R8(d, 112), R8(d, 120), "+r"(r.n) \
    : "l"(ha), "l"(hb), "r"(r.full), "r"(r.rel), "r"((uint32_t)r.sig), "r"(wg), \
      "n"(SB0 / 16 + (TA ? 32 << 16 : 1 << 16)), "n"(TA ? 128 : 2), "n"(SB0 / 16 + 1024 + (1 << 16)), "n"(TA), "n"(SPIN_LIMIT) P4O \
    : "memory"
#define STEP_REGS "{.reg .b32 k, t, ph, hb; .reg .b64 da, db; .reg .pred ps, pl, pa, pr;\n" P4I "setp.ne.u32 ps, %133, 0;\n"
#define FIRST_WAIT "FIRST: mbarrier.try_wait.parity.shared::cta.b64 pk, [t], ph; @pk bra START; add.u32 %128, %128, 1; setp.le.u32 pk, %128, %139; @pk bra FIRST; START:\n"
__device__ __forceinline__ void gemm1(float (&d)[128], Ring& r, uint64_t ha, uint64_t hb, int wg) {
    asm volatile(STEP_REGS "mul.lo.u32 k, %134, 15; mov.b32 ph, %134; setp.ne.u32 pl, k, 0; mad.lo.u32 t, %134, 8, %131;\n"
                 "pmevent 1; @pl bar.sync 1, 256;\n" FIRST_WAIT "@pl bra ONE;\n"
                 "LOOP: setp.ne.u32 pa, k, 0; and.pred pr, pa, ps; setp.eq.u32 pl, k, 15;\n"
                 STEP(0, 4, 1, ph, pa, pr, "@pl bar.arrive 1, 256;\n", "@pl bra END;\n")
                 "ONE: setp.ne.u32 pa, k, 15; and.pred pr, pa, ps; setp.eq.u32 pl, k, 30;\n"
                 STEP(1, 0, 2, ph, pa, pr, "@pl bar.arrive 2, 256;\n", "@pl bra END;\n")
                 STEP(2, 1, 3, ph, 1, ps, "", "") STEP(3, 2, 4, ph, 1, ps, "", "") "xor.b32 ph, ph, 1; add.u32 k, k, 5;\n" STEP(4, 3, 0, ph, 1, ps, "", "")
                 "bra LOOP;\n"
                 "END:\n" P4B "}" STEP_ARGS(0));
}
__device__ __forceinline__ void gemm2(float (&d)[128], Ring& r, uint64_t ha, uint64_t hb, int wg) {
    asm volatile(STEP_REGS "mov.b32 k, 0; mov.b32 ph, 0; add.u32 t, %131, 16;\n"
                 "pmevent 1; bar.sync 2, 256;\n" FIRST_WAIT
                 "LOOP: setp.ne.u32 pa, k, 0; and.pred pr, pa, ps; setp.eq.u32 pl, k, 5;\n"
                 STEP(2, 1, 3, ph, pa, pr, "", "") STEP(3, 2, 4, ph, 1, ps, "", "") "xor.b32 ph, ph, 1; add.u32 k, k, 1;\n" STEP(4, 3, 0, ph, 1, ps, "", "")
                 "@pl bra END;\n" STEP(0, 4, 1, ph, 1, ps, "", "") STEP(1, 0, 2, ph, 1, ps, "", "")
                 "bra LOOP;\n"
                 "END: }" STEP_ARGS(1));
}
template <int O, int K, int J> __device__ __forceinline__ void mma_h(float (&y)[128], uint64_t a, uint64_t b) { mma128_ss<O, 1, 0>(y, a + SL(K) * 2048 + O * 8 + 128 * J, b + SL(K) * 2048 + 2 * J, 1); }
template <int O, int K> __device__ __forceinline__ void half_step(float (&y)[128], uint64_t a, uint64_t b) { mma_h<O, K, 0>(y, a, b); mma_h<O, K, 1>(y, a, b); mma_h<O, K, 2>(y, a, b); mma_h<O, K, 3>(y, a, b); }
template <int R, int U> __device__ __forceinline__ void out_piece(float (&y)[128], const uint32_t (&dd)[16], uint32_t x0, uint32_t x1, float* op) {
    const int i = 64 * (R >> 1) + 8 * U + 2 * (R & 1);
    asm("mul.rn.bf16x2 %0, %0, %1;" : "+r"(x0) : "r"(dd[2 * U]));
    asm("mul.rn.bf16x2 %0, %0, %1;" : "+r"(x1) : "r"(dd[2 * U + 1]));
    asm volatile("st.global.v4.f32 [%0], {%1,%2,%3,%4};" ::"l"(op + (32 * (R & 1) + 16 * (R >> 1)) * 2048 + 16 * U),
                 "f"(y[i] + __uint_as_float(x0 << 16)), "f"(y[i + 1] + __uint_as_float(x0 & 0xffff0000u)),
                 "f"(y[i + 4] + __uint_as_float(x1 << 16)), "f"(y[i + 5] + __uint_as_float(x1 & 0xffff0000u)) : "memory");
}
template <int R, int U0> __device__ __forceinline__ void load_x4(uint32_t (&xx)[8], uint32_t xa) {
#pragma unroll
    for (int u = 0; u < 4; u++)
        asm volatile("ld.shared.v2.b32 {%0,%1}, [%2];" : "=r"(xx[2 * u]), "=r"(xx[2 * u + 1]) : "r"((xa ^ (u << 5)) + (3 - R) * 8192 + U0 * 1024) : "memory");
}
__device__ __forceinline__ Ring ring_at(uint32_t sb, int k) {
    Ring r;
    r.n = 0;
    r.full = sb + OFF_BAR + B_FULL;
    asm("mapa.shared::cluster.u32 %0, %1, %2;" : "=r"(r.rel) : "r"(sb + OFF_BAR + B_EMPTY), "r"((threadIdx.x >> 5) & 1));
    r.sig = __shfl_sync(~0u, threadIdx.x & 95, threadIdx.x) == 0;
    return r;
}

template <bool BY_SM> __global__ void __cluster_dims__(2, 1, 1) __launch_bounds__(512, 1)
fused_kernel(const __grid_constant__ CUtensorMap tmX, const __grid_constant__ CUtensorMap tmBre, const __grid_constant__ CUtensorMap tmBim,
             const __grid_constant__ CUtensorMap tmCre, const __grid_constant__ CUtensorMap tmCim, const __grid_constant__ CUtensorMap tmXd,
             const __grid_constant__ CUtensorMap tmUst, const __grid_constant__ CUtensorMap tmVst,
             const __grid_constant__ CUtensorMap tmWr, const __grid_constant__ CUtensorMap tmWi, const __grid_constant__ CUtensorMap tmXa,
             const Params p) {
    extern __shared__ __align__(1024) uint8_t smraw[];
    asm volatile(".reg .pred pk, p0;");
    const int tid = threadIdx.x, rank = blockIdx.x & 1;
    const uint32_t wi = __shfl_sync(~0u, smem_u32(smraw) + (tid >> 5), 0), sb = wi & ~15u, bars = sb + OFF_BAR;
    const int wg = (wi >> 2) & 3, w = wi & 3, lane = tid & 31, g = lane >> 2, q = lane & 3;
    if (wg != 3) asm volatile("barrier.cluster.arrive.relaxed.aligned; barrier.cluster.wait.aligned;" ::: "memory");
    else asm volatile("prefetch.tensormap [%0];" ::"l"(w == 0 ? &tmX : w == 1 ? &tmBre : &tmBim) : "memory");
    int role;
    {
        uint32_t T = blockIdx.x;
        if (BY_SM) asm("mov.u32 %0, %%smid;" : "=r"(T));
        T >>= 1;
        const uint32_t a = ((T - 32) * 37) >> 8;
        asm("{.reg .pred p; setp.lt.u32 p, %1, 62; selp.u32 %0, 4, -58, p; add.u32 %0, %0, %1;\n"
            "setp.lt.u32 p, %1, 60; selp.u32 %0, %2, %0, p; setp.lt.u32 p, %1, 32; selp.u32 %0, %3, %0, p;}"
            : "=&r"(role) : "r"(T), "r"(8 * (T - 31 - 7 * a) + 4 + a), "r"(8 * (T & 7) + (T >> 3)));
        role = 2 * role + rank;
    }
    const bool spare = role >= 128;
    const int tc = ((role >> 3) & 14) + rank, cb = (role >> 1) & 7;
    const int fb = role >> 5, fcb = role & 31, fpos = pos_of(fcb);
    const int nu = role == 128 ? 1 : (fcb || !role ? 2 : 0);

    if (wg == 3) {
        if (elect_one()) {
            const uint32_t b = bars + w * 8;
            STAMP5(57);
            mbar_init(b, 1);
            if (w < 3 && !spare) {
                mbar_expect_tx(b, 32768);
                tma5d(sb + w * 32768 + 16384, &tmX, w * 64, 0, 0, 0, tc, b);
                if (w == 0) { tma4d(sb, &tmBre, 0, 0, 0, cb * 4, b); tma4d(sb + 8192, &tmBim, 0, 0, 0, cb * 4, b); }
                STAMP5(58);
            }
#pragma unroll
            for (int o = 32; o < B_EPOCH; o += 32) mbar_init(b + o, o < B_EMPTY ? 1 : (o < B_STG ? 2 : (o < B_P3M ? 4 : 8)));
            asm volatile("fence.mbarrier_init.release.cluster;" ::: "memory");
        }
        __syncwarp();
        STAMP5(59);
        asm volatile("barrier.cluster.arrive.relaxed.aligned;" ::: "memory");
    }
    if (opaque32(wg) == 3) {
        asm volatile("setmaxnreg.dec.sync.aligned.u32 24;");
        asm volatile("barrier.cluster.wait.aligned;" ::: "memory");
        if (w == 0) {
            if (!spare && elect_one()) {
                STAMP(56);
#pragma unroll 1
                for (int k = 1; k < NST; k++) {
                    if (k >= 3) mbar_expect_tx(bars + B_FULL + k * 8, 32768);
                    tma4d_mc(sb + k * 32768 + rank * 8192, rank ? &tmBim : &tmBre, k * 64, 0, 0, cb * 4, bars + B_FULL + k * 8);
                    if (k >= 3) tma5d(sb + k * 32768 + 16384, &tmX, k * 64, 0, 0, 0, tc, bars + B_FULL + k * 8);
                }
#define RING_WAIT "mbarrier.try_wait.parity.shared::cta.b64 p, [fb + 256], ph; @p bra GO;\n" \
                  "WAIT: mbarrier.try_wait.parity.shared::cta.b64 p, [fb + 256], ph; add.u32 n, n, 1; setp.gt.or.u32 p, n, 32768, p; @!p bra WAIT;\nGO:\n"
#define RING_NEXT "pmevent 1; add.u32 o, o, 8; setp.eq.u32 p, o, 40; selp.u32 o, 0, o, p; @p xor.b32 ph, ph, 1; add.u32 fb, %1, o; shl.b32 t, o, 12; add.u32 da, %0, t;\n"
                asm volatile("{.reg .b32 o, k, kk, c2, da, db, fb, ph, n, t; .reg .pred p;\n"
                             "mov.b32 o, 0; mov.b32 k, 320; mov.b32 kk, 320; mov.b32 c2, 0; mov.b32 ph, 0; mov.b32 n, 0; mov.b32 fb, %1; mov.b32 da, %0; mov.b32 db, %2;\n"
                             "LOOP:\n" RING_WAIT
                             "cp.async.bulk.tensor.5d.shared::cluster.global.mbarrier::complete_tx::bytes [da], [%3, {kk,0,0,0,%5}], [fb];\n"
                             "cp.async.bulk.tensor.4d.shared::cluster.global.mbarrier::complete_tx::bytes.multicast::cluster [db], [%4, {kk,0,c2,%6}], [fb], %7;\n"
                             "mbarrier.arrive.expect_tx.shared::cta.b64 _, [fb], 32768;\n" RING_NEXT
                             "add.u32 db, %2, t; add.u32 k, k, 64; and.b32 kk, k, 1023; shr.u32 c2, k, 9; and.b32 c2, c2, 2; setp.ne.u32 p, k, 2048; @p bra LOOP;}"
                             ::"r"(sb + 16384), "r"(bars + B_FULL), "r"(sb + rank * 8192), "l"(&tmX), "l"(rank ? &tmBim : &tmBre), "r"(tc), "r"(cb * 4), "h"((uint16_t)3) : "memory");
                asm volatile("{.reg .b32 o, k, kk, da, db, fb, hb, ph, n, t; .reg .b64 m, src; .reg .pred p;\n"
                             "mov.b32 o, 16; mov.b32 k, 0; mov.b32 kk, 0; mov.b32 ph, 1; mov.b32 n, 0; add.u32 fb, %1, 16; add.u32 hb, %1, 72; add.u32 da, %0, 65536; add.u32 db, %2, 65536;\n"
                             "mov.b64 m, %3; mov.b64 src, %5;\n"
                             "GROUP: add.u32 t, %8, k;\n"
                             "OWN: mbarrier.try_wait.parity.shared::cta.b64 p, [t], 0; add.u32 n, n, 1; setp.gt.or.u32 p, n, 32768, p; @!p bra OWN;\n"
                             "LOOP:\n" RING_WAIT
                             "cp.async.bulk.shared::cluster.global.mbarrier::complete_tx::bytes [da], [src], 16384, [hb];\n"
                             "cp.async.bulk.tensor.5d.shared::cluster.global.mbarrier::complete_tx::bytes.multicast::cluster [db], [m, {kk,0,0,0,%6}], [fb], %7;\n"
                             "mbarrier.expect_tx.shared::cta.b64 [fb], 16384; mbarrier.arrive.expect_tx.shared::cta.b64 _, [hb], 16384;\n" RING_NEXT
                             "add.u32 db, %2, t; add.u64 src, src, 16384; sub.u64 m, %4, m; add.u32 k, k, 1; shl.b32 kk, k, 5; and.b32 kk, kk, 0x7c0;\n"
                             "and.b32 t, k, 1; mad.lo.u32 hb, t, 8, fb; add.u32 hb, hb, o; add.u32 hb, hb, 40;\n"
                             "and.b32 t, k, 7; setp.ne.u32 p, t, 0; @p bra LOOP; setp.ne.u32 p, k, 32; @p bra GROUP;}"
                             ::"r"(sb), "r"(bars + B_FULL), "r"(sb + 16384 + rank * 8192), "l"(&tmCre), "l"((uint64_t)&tmCre + (uint64_t)&tmCim),
                               "l"(g_H + (size_t)tc * 32 * 16384), "r"(cb * 8 + rank * 4), "h"((uint16_t)3), "r"(bars + B_HOWN) : "memory");
            }
        } else if (opaque32(w) == 1) {
            const unsigned ep = ld_rlx(g_epoch + role * 8) + 1;
            __syncwarp();
            if (elect_one()) {
                asm volatile("st.relaxed.gpu.global.u32 [%0], %1;" ::"l"(g_epoch + role * 8), "r"(ep) : "memory");
                asm volatile("st.shared.u32 [%0], %1;" ::"r"(bars + B_EPOCH), "r"(ep) : "memory");
                mbar_arrive(bars + B_EP);
            }
            int slot;
            const int kap = unit_of(role, 0, slot), kap1 = unit_of(role, 1, slot);
            uint32_t lph = 0;
            if (!spare) mbar_wait(bars + B_STGU, 0);
            STAMP(21);
            const int c0 = fb * 2048 + fpos * 64;
            if (elect_one()) {
                if (!spare) {
#pragma unroll 1
                    for (int r = 4; r < 8; r++) bulk_st(g_X + r * (32 * 16384) + c0 * 2, sb + OFF_P + r * 4096, 128);
                    tma2d_st(&tmUst, c0, 0, sb + OFF_P);
                    bulk_commit();
                    tma2d_st(&tmUst, c0, 64, sb + OFF_P + 8192);
                    bulk_commit();
                    asm volatile("cp.async.bulk.wait_group.read 1;" ::: "memory");
                    red_hint(g_cnt);
                }
                mbar_expect_tx(bars + B_FG, 8192);
                bulk_ld(sb + OFF_F, (const uint8_t*)g_tab + TAB_FG, 8192, bars + B_FG);
            }
            STAMP(40);
#pragma unroll 1
            for (int e = 0; e < 4; e++) {
                if (e >= 2) {
                    if (e == nu) {
                        mbar_wait(bars + B_WFREE, 0);
                        if (elect_one()) load_w_rows(sb + OFF_WD, &tmWr, &tmWi, kap1, bars + B_WD);
                    }
                    if (e - 2 < nu) mbar_wait(bars + B_STG, e & 1);
                    STAMPO(23, e - 2);
                    if (e == nu && elect_one()) {
                        const int c = (role ? slot : 256) * 32;
                        tma2d_st(&tmVst, c, 0, sb + OFF_P);
                        tma2d_st(&tmVst, c + 4096, 0, sb + OFF_P + 8192);
                        bulk_commit();
                        if (role) { bulk_wait_read(); red_hint(g_cnt + 64); } else bulk_wait_all();
                    }
                    if (e == 3 && !spare && elect_one()) {
                        mbar_expect_tx(bars + B_FG, 8192);
                        bulk_ld(sb + OFF_F, (const uint8_t*)g_tab + TAB_G + fb * 8192, 8192, bars + B_FG);
                    }
                }
                const uint32_t tg = e < 2 ? lane * 128 + ((((lane >> 1) & 2) ^ (lane & 3)) << 4) + (lane >> 3) * 4 : lane * 64 + (lane & 8) * 4 + (lane & 2) * 8 + (lane & 4) * 2;
                if (spare) {
                    if (e == 1) {
                        wait_cnt(g_cnt, 128 * ep);
                        STAMP(42);
#pragma unroll 1
                        for (int n = 0; n < 4096; n++) {
                            if (elect_one()) {
                                mbar_expect_tx(bars + B_LD, 8 * 16384);
#pragma unroll 1
                                for (int r = 0; r < 8; r++) bulk_ld(sb + r * 16384, g_X + (size_t)r * (32 * 16384), 16384, bars + B_LD);
                            }
                            mbar_wait(bars + B_LD, n & 1);
                            bool ok = true;
#pragma unroll 1
                            for (int r = 0; r < 8; r++) ok &= tags_ok<4096>(sb + r * 16384 + tg, ep);
                            if (ok) break;
                        }
                        if (elect_one()) mbar_arrive(bars + B_RAW);
                    }
                } else {
                    const uint32_t dst = sb + OFF_P + (e & 1) * 16384;
#define X_ST1
#define X_ST2
#define X_RETRY
#define X_ARG
                    asm volatile("{.reg .b32 n, a, v0, v1, v2, v3; .reg .pred p, pe, pu;\n"
                                 "elect.sync _|pe, 0xffffffff; setp.lt.u32 pu, %10, 2; mov.b32 n, 0; pmevent 1;\n"
                                 "POLL: ld.relaxed.gpu.global.u32 v0, [%1]; setp.eq.u32 p, v0, %2; @p bra LOAD;\n"
                                 "nanosleep.u32 20; add.u32 n, n, 1; setp.lt.u32 p, n, 32768; @p bra POLL;\n"
                                 "LOAD:\n" X_ST1 "cp.async.bulk.wait_group.read 0;\n"
                                 "@pe cp.async.bulk.shared::cluster.global.mbarrier::complete_tx::bytes [%3], [%4], 16384, [%5]; @pe mbarrier.arrive.expect_tx.shared::cta.b64 _, [%5], 16384;\n"
                                 "mov.b32 a, 0;\n"
                                 "WAIT: mbarrier.try_wait.parity.shared::cta.b64 p, [%5], %0; @p bra CHECK; add.u32 n, n, 1; setp.lt.u32 p, n, 65536; @p bra WAIT;\n"
                                 "CHECK:\n" X_ST2 "@pu bra FOUR;\n"
                                 "ld.shared.u32 a, [%7]; ld.shared.u32 v0, [%6 + 2048]; ld.shared.u32 v1, [%6 + 6144]; ld.shared.u32 v2, [%6 + 10240]; ld.shared.u32 v3, [%6 + 14336];\n"
                                 "lop3.b32 a, a, v0, %8, 0x7e; lop3.b32 v1, v1, v2, %8, 0x7e; lop3.b32 a, a, v3, %8, 0xf6; or.b32 a, a, v1;\n"
                                 "FOUR: ld.shared.u32 v0, [%6]; ld.shared.u32 v1, [%6 + 4096]; ld.shared.u32 v2, [%6 + 8192]; ld.shared.u32 v3, [%6 + 12288];\n"
                                 "lop3.b32 a, a, v0, %8, 0xf6; lop3.b32 a, a, v1, %8, 0xf6; lop3.b32 v2, v2, v3, %8, 0x7e; lop3.b32 a, a, v2, 1, 0xa8;\n"
                                 "setp.eq.u32 p, a, 0; vote.sync.all.pred p, p, -1; @p bra OK;\n" X_RETRY
                                 "add.u32 n, n, 16; setp.ge.u32 p, n, 65536; @p bra OK; xor.b32 %0, %0, 1; bra LOAD;\n"
                                 "OK: @pe mbarrier.arrive.shared::cta.b64 _, [%9]; pmevent 1; xor.b32 %0, %0, 1;}"
                                 : "+r"(lph)
                                 : "l"(g_cnt + e * 32), "r"(128 * ep), "r"(dst), "l"(g_X + (size_t)(e < 2 ? role + e * 128 : 254 + (fb * 32 + fpos) * 2 + e) * 16384), "r"(bars + B_LD),
                                   "r"(dst + tg), "r"(dst + (e == 3 ? (lane & 1) * 8192 + 32 : 0)), "r"(ep), "r"(bars + B_IN + e * 8), "r"(e) X_ARG : "memory");
                }
                if (e < 2 && elect_one()) {
                    if (e) prefetch_w_rows(&tmWr, &tmWi, kap1);
                    else {
                        if (nu) load_w_rows(sb + OFF_WD, &tmWr, &tmWi, kap, bars + B_WD);
                        if (!spare) {
                            tma2d_st(&tmUst, c0, 128, sb + OFF_P + 16384);
                            tma2d_st(&tmUst, c0, 192, sb + OFF_P + 24576);
                            bulk_commit();
                            bulk_wait_read();
                            red_hint(g_cnt + 32);
                        }
                    }
                }
            }
            if (!spare) {
                mbar_wait(bars + B_HOWN + 8, 0);
#pragma unroll 1
                for (int r = 0; r < 4; r++) {
                    if (r == 3) mbar_wait(bars + B_P3M, 0);
                    if (elect_one()) {
                        if (r == 0) { mbar_expect_tx(bars + B_XD, 24576 + 256); mbar_expect_tx(bars + B_XD + 8, 8192); bulk_ld(sb + OFF_LAM, p.dsk + cb * 128, 256, bars + B_XD); }
                        tma4d(sb + OFF_F + (3 - r) * 8192, &tmXd, 0, tc * 128 + 32 * (r & 1) + 16 * (r >> 1), 0, cb * 2, bars + B_XD + (r == 3) * 8);
                    }
                    __nanosleep(PACE_X);
                }
            }
        } else {
            if (w == 2) {
                {
                    const int u = lane >> 4;
                    int slot;
                    const int r0 = unit_of(role, u, slot) + 512 * ((lane >> 1) & 3), r1 = (2048 - r0) & 2047, mir = (lane >> 3) & 1;
                    const unsigned short* wp = (const unsigned short*)((lane & 1) ? p.wi : p.wr);
                    const float a = bf2f(wp[r0 * 513 + mir * 512]), b = bf2f(wp[r1 * 513 + mir * 512]);
                    asm volatile("st.shared.f32 [%0], %1;" ::"r"(sb + OFF_WSP + u * 64 + (lane & 15) * 4), "f"(0.5f * ((lane & 1) ? (mir ? b - a : a - b) : a + b)) : "memory");
                }
                warp_arrive(bars + B_WSP);
            } else if (!spare) {
#pragma unroll 1
                for (int i = 0; i < 8; i++) {
                    if (i >= XA_N0) __nanosleep(XA_PACE);
                    if (elect_one()) {
                        const uint32_t xb = bars + (i < 4 ? B_RAW : B_XIN);
                        if (!(i & 3)) mbar_expect_tx(xb, 16384);
                        tma3d(sb + OFF_F + i * 4096, &tmXa, fcb * 32, 0, 4 * i + fb, xb);
                    }
                }
            }
            if (!spare) {
                if (w == 2 && nu) {
                    int slot;
                    const int kap = unit_of(role, 0, slot);
                    mbar_wait(bars + B_XIN, 0);
                    if (elect_one()) prefetch_w_rows(&tmWr, &tmWi, kap);
                }
                const unsigned ep = get_epoch(bars);
#define CNT_RETRY
#define CNT_ARG
                asm volatile("{.reg .b32 o, k, hb, fb, ca, m, ph, rph, n, t, v0, v1, v2, v3; .reg .b64 src; .reg .pred p, pe;\n"
                             "elect.sync _|pe, 0xffffffff; mov.b32 o, %0; shr.u32 k, %0, 3; sub.u32 k, k, 2; mov.b32 m, 0x107c0; mov.b32 rph, 0; mov.b32 n, 0;\n"
                             "bra NEXT;\n"
                             "LOOP: mbarrier.try_wait.parity.shared::cta.b64 p, [hb], ph; @p bra GO;\n"
                             "WAIT: mbarrier.try_wait.parity.shared::cta.b64 p, [hb], ph; add.u32 n, n, 1; setp.gt.or.u32 p, n, 32768, p; @!p bra WAIT;\n"
                             "GO: ld.shared.u32 v0, [ca]; ld.shared.u32 v1, [ca + 128]; ld.shared.u32 v2, [ca + 256]; ld.shared.u32 v3, [ca + 384];\n"
                             "lop3.b32 v0, v0, v1, %4, 0x7e; lop3.b32 v2, v2, v3, %4, 0x7e; lop3.b32 v0, v0, v2, 1, 0xa8; setp.eq.u32 p, v0, 0; vote.sync.all.pred p, p, -1; @p bra OK;\n"
                             CNT_RETRY "add.u32 n, n, 16; setp.gt.u32 p, n, 32768; @p bra OK;\n"
                             "shl.b32 t, o, 12; add.u32 t, t, %5; mad.wide.u32 src, k, 16384, %6;\n"
                             "@pe mbarrier.arrive.expect_tx.shared::cta.b64 _, [%7], 16384; @pe cp.async.bulk.shared::cluster.global.mbarrier::complete_tx::bytes [t], [src], 16384, [%7];\n"
                             "AGAIN: mbarrier.try_wait.parity.shared::cta.b64 p, [%7], rph; add.u32 n, n, 1; setp.gt.or.u32 p, n, 32768, p; @!p bra AGAIN;\n"
                             "xor.b32 rph, rph, 1; bra GO;\n"
                             "OK: @pe mbarrier.arrive.shared::cta.b64 _, [fb]; pmevent 1;\n"
                             "add.u32 o, o, 16; setp.ge.u32 p, o, 40; @p sub.u32 o, o, 40; add.u32 k, k, 2;\n"
                             "NEXT: shr.u32 m, m, 1; and.b32 ph, m, 1; add.u32 fb, %1, o; mad.lo.u32 hb, o, 2, %2; mad.lo.u32 ca, o, 4096, %3; setp.lt.u32 p, k, 32; @p bra LOOP;}"
                             ::"r"(8 * w), "r"(bars + B_FULL), "r"(bars + B_HL - 16 + w * 8), "r"(sb + (q >> 1) * 8192 + (q & 1) * 512 + g * 1040 + q * 4), "r"(ep),
                               "r"(sb), "l"(g_H + (size_t)tc * 32 * 16384), "r"(bars + B_HR - 16 + w * 8) CNT_ARG : "memory");
                if (w == 3) warp_arrive(bars + B_DONE);
            }
        }
    } else {
        STAMP(55);
        asm volatile("setmaxnreg.inc.sync.aligned.u32 152;");
        STAMP5(60);
        const int t7 = tid & 127, hf = wg - 1;
        const int mi = lane >> 3, gl = lane & 7;
        if (spare && wg != 2) {
            if (tid < 64) { const uint4 v = __ldg((const uint4*)((const uint8_t*)g_tab + TAB_PC) + tid); sts128(sb + OFF_LAM + tid * 16, v.x, v.y, v.z, v.w); }
            bar_sync(1, 256);
            mbar_wait(bars + B_RAW, 0);
            STAMP(0);
#pragma unroll 1
            for (int u = 0; u < nu; u++) {
                int slot;
                const int t = unit_of(role, u, slot) >> 5;
                const uint32_t off = (tid >> 2) * 128 + q * 16;
                float zr[16], zi[16];
#pragma unroll
                for (int k = 0; k < 16; k++) zr[k] = zi[k] = 0.f;
#pragma unroll 1
                for (int r = (t & 1) ? 0 : t >> 1; r < 8 - ((t & 1) ? 0 : (t >> 1) - 1); r += (t & 1) ? 1 : 8 - t) {
                    float4 c;
                    float a[8], b[8];
                    lds128f(sb + OFF_LAM + t * 128 + r * 16, c.x, c.y, c.z, c.w);
                    lds128f(sb + r * 16384 + off, a[0], a[1], a[2], a[3]);
                    lds128f(sb + r * 16384 + off + 64, b[0], b[1], b[2], b[3]);
                    lds128f(sb + r * 16384 + off + 8192, a[4], a[5], a[6], a[7]);
                    lds128f(sb + r * 16384 + off + 8192 + 64, b[4], b[5], b[6], b[7]);
#pragma unroll
                    for (int k = 0; k < 16; k++) {
                        const uint32_t ua = __float_as_uint(a[k >> 1]), ub = __float_as_uint(b[k >> 1]);
                        const float x = __uint_as_float((k & 1) ? ua & 0xffff0000u : ua << 16), y = __uint_as_float((k & 1) ? ub & 0xffff0000u : ub << 16);
                        zr[k] = fmaf(c.x, x, fmaf(c.z, y, zr[k]));
                        zi[k] = fmaf(c.y, x, fmaf(c.w, y, zi[k]));
                    }
                }
                const uint32_t dst = sb + OFF_P + u * 16384 + off;
#pragma unroll
                for (int k = 0; k < 16; k += 8) {
                    sts128(dst + k * 1024, pk(zr[k], zr[k + 1]), pk(zr[k + 2], zr[k + 3]), pk(zr[k + 4], zr[k + 5]), pk(zr[k + 6], zr[k + 7]));
                    sts128(dst + k * 1024 + 64, pk(zi[k], zi[k + 1]), pk(zi[k + 2], zi[k + 3]), pk(zi[k + 4], zi[k + 5]), pk(zi[k + 6], zi[k + 7]));
                }
                fence_async_sm();
                bar_sync(1, 256);
                if (tid == 0) mbar_arrive(bars + B_IN + u * 8);
                STAMPO(1, u);
            }
            return;
        }
        if (wg == 2 && !spare) {
            asm volatile("setmaxnreg.inc.sync.aligned.u32 176;");
            uint32_t f1[16];
            cf tw[8];
            if (TAB_T0) __nanosleep(TAB_T0);
            ldtab<4, 2048>(f1, TAB_F1 + t7 * 16);
            ldtab_cf<16>(tw, TAB_TW1 + (t7 >> 2) * 64);
            const uint32_t ep = get_epoch(bars);
            uint32_t a0 = sb + OFF_P + (8 * w + gl + 32 * (mi >> 1)) * 128 + (((((mi & 1) << 2) | (fpos & 3)) ^ gl) << 4);
            float acc[128];
            const uint64_t dx = opaque(mkdesc(sb + OFF_F, 4096, 512, 2));
            mbar_wait(bars + B_RAW, 0);
            pinu(f1);
            wg_fence();
#pragma unroll
            for (int j = 0; j < 4; j++) mma128_rs<0, 1>(acc, f1[4 * j], f1[4 * j + 1], f1[4 * j + 2], f1[4 * j + 3], dx + j * 64, j);
            wg_commit();
            mbar_wait(bars + B_XIN, 0);
            wg_fence();
            STAMP(20);
#pragma unroll
            for (int j = 0; j < 4; j++) mma128_rs<64, 1>(acc, f1[4 * j], f1[4 * j + 1], f1[4 * j + 2], f1[4 * j + 3], dx + 1024 + j * 64, j);
            wg_commit();
            wg_wait<0>();
            pin(acc);
            pinu(f1);
#pragma unroll 1
            for (int h = 0;; h++) {
                const uint32_t tmask = 2 * q + h == fpos >> 2 ? ~1u : ~0u, tbit = ep & ~tmask;
#pragma unroll
                for (int cl = 0; cl < 2; cl++) {
                    c2 v[8];
#pragma unroll
                    for (int n = 0; n < 8; n++) {
                        const int i = 4 * (4 * n + cl);
                        v[n] = {{acc[i], acc[i + 2]}, {acc[i + 1], acc[i + 3]}};
                    }
                    dft8<true, YP1>(v, tw);
#pragma unroll
                    for (int r = 0; r < 8; r += 2) {
                        uint32_t o0 = pk(v[r].a.x, v[r].b.x), o1 = pk(v[r].a.y, v[r].b.y), o2 = pk(v[r + 1].a.x, v[r + 1].b.x), o3 = pk(v[r + 1].a.y, v[r + 1].b.y);
                        if (cl == 0) { o0 = (o0 & tmask) | tbit; o2 = (o2 & tmask) | tbit; }
                        stsm4((a0 ^ (cl << 4)) + r * 4096, o0, o1, o2, o3);
                    }
                }
                if (h) break;
                a0 ^= 32;
#pragma unroll
                for (int n = 0; n < 8; n++) {
                    asm volatile("mov.b32 %0, %8; mov.b32 %1, %9; mov.b32 %2, %10; mov.b32 %3, %11; mov.b32 %4, %12; mov.b32 %5, %13; mov.b32 %6, %14; mov.b32 %7, %15; pmevent 1;"
                                 : "=&f"(acc[16 * n]), "=&f"(acc[16 * n + 1]), "=&f"(acc[16 * n + 2]), "=&f"(acc[16 * n + 3]), "=&f"(acc[16 * n + 4]), "=&f"(acc[16 * n + 5]), "=&f"(acc[16 * n + 6]), "=&f"(acc[16 * n + 7])
                                 : "f"(acc[16 * n + 8]), "f"(acc[16 * n + 9]), "f"(acc[16 * n + 10]), "f"(acc[16 * n + 11]), "f"(acc[16 * n + 12]), "f"(acc[16 * n + 13]), "f"(acc[16 * n + 14]), "f"(acc[16 * n + 15]));
                }
            }
            fence_async_sm();
            warp_arrive(bars + B_STGU);
            bar_sync(3, 128);
            asm volatile("setmaxnreg.dec.sync.aligned.u32 152;");
            bar_arrive(7, 256);
        }
        if (wg == 1) {
            if (LAM_T0) __nanosleep(LAM_T0);
            const int cl = tid & 127, ch = (cl >> 6) * 512 + ((cl >> 3) & 1) * 256 + cb * 32 + ((cl >> 4) & 3) * 8 + (cl & 7);
            const float lr = bf2f(*(const unsigned short*)padd(p.lre, 2 * ch)), li = bf2f(*(const unsigned short*)padd(p.lim, 2 * ch));
            const float dt = __bfloat162float(__float2bfloat16(expf(bf2f(*(const unsigned short*)padd(p.ldt, 2 * ch)))));
            const float an = dt * li, th = an * 0.318309873342514f;
            float sn, cs, inv;
            sincospif(fmaf(rintf(0.5f * th), -2.f, th) + fmaf(an, 1.2841276653e-8f, fmaf(an, 0.318309873342514f, -th)), &sn, &cs);
            const float ex = expf(dt * lr), br = ex * cs, bi = ex * sn;
            asm("rcp.approx.f32 %0, %1;" : "=f"(inv) : "f"(lr * lr + li * li));
            inv += inv;
            const float cr = ((br - 1.f) * lr + bi * li) * inv, ci = (bi * lr - (br - 1.f) * li) * inv;
            sts128(sb + OFF_LAM + cl * 16, __float_as_uint(br), __float_as_uint(-bi), __float_as_uint(cr), __float_as_uint(-ci));
            mbar_wait(bars + B_EP, 0);
            bar_sync(8, 128);
            if (tid == 128) mbar_arrive(bars + B_LAM);
        }
        if (wg != 2) {
        if (wg == 0) bar_sync(4, 128); else bar_sync(7, 256);
        asm volatile("setmaxnreg.inc.sync.aligned.u32 160;");
        if (wg == 0) bar_sync(4, 128);
        float d[128];
        STAMPW(0, 10);
        Ring rg = ring_at(sb, role * 66 + wg * 16);
        cf lam[2];
        unsigned ep;
        gemm1(d, rg, ring_desc(sb, 0, 16, 1), ring_desc(sb, 16384, 16, 1), wg);
        const uint32_t lama = sb + OFF_LAM + wg * 1024 + w * 256 + (fresh_lane() & 28) * 4;
        mbar_wait_fast(bars + B_LAM, 0);
        lam[0] = lds_cf(lama); lam[1] = lds_cf(lama + 128);
        asm volatile("ld.shared.u32 %0, [%1];" : "=r"(ep) : "r"(bars + B_EPOCH) : "memory");
        asm volatile("setmaxnreg.inc.sync.aligned.u32 176;");
        cf L[2] = {lam[0], lam[1]};
#pragma unroll
        for (int i = 0; i < 4; i++) { L[0] = csq(L[0]); L[1] = csq(L[1]); }
        asm volatile("" : "+f"(L[0].x), "+f"(L[0].y), "+f"(L[1].x), "+f"(L[1].y)::"memory");
        wg_wait<0>();
        ring_release(rg, 8 * wg);
        pin(d);
        STAMPW(1, 11);
        {
            const int lane = fresh_lane(), g = lane >> 2, q = lane & 3, mi = lane >> 3, gl = lane & 7;
            cf f[2], fb2[2];
#pragma unroll
            for (int i = 0; i < 17; i++) {
#pragma unroll
                for (int h = 0; h < 2; h++) {
                    const int r = 4 * (i >> 1) + 2 * h + (i & 1), r2 = 32 + 4 * ((i - 1) >> 1) + 2 * h + ((i - 1) & 1);
                    if (i < 16) f[h] = i ? cfma(lam[h], f[h], {d[r], -d[64 + r]}) : cf{d[r], -d[64 + r]};
                    if (i > 0) fb2[h] = i > 1 ? cfma(lam[h], fb2[h], {d[r2], -d[64 + r2]}) : cf{d[r2], -d[64 + r2]};
                    if (i && (h || !(YS & 8))) YIELD_S1();
                }
            }
            const uint8_t* cbase = (const uint8_t*)g_carry + (tc * 16 + wg * 8 + cb) * 512 + w * 64;
            const uint8_t* cptr = padd(cbase, g * 8);
            const unsigned tag = ep & 15u;
#pragma unroll
            for (int h = 0; h < 2; h++) { f[h] = cfma(L[h], f[h], fb2[h]); L[h] = csq(L[h]); }
            cf s0[2], s1[2], s2[2];
#pragma unroll
            for (int h = 0; h < 2; h++) {
                s0[h] = {__shfl_sync(~0u, f[h].x, 0, 4), __shfl_sync(~0u, f[h].y, 0, 4)};
                s1[h] = {__shfl_sync(~0u, f[h].x, 1, 4), __shfl_sync(~0u, f[h].y, 1, 4)};
                s2[h] = {__shfl_sync(~0u, f[h].x, 2, 4), __shfl_sync(~0u, f[h].y, 2, 4)};
            }
#pragma unroll
            for (int h = 0; h < 2; h++) {
                s1[h] = cfma(L[h], s0[h], s1[h]);
                s2[h] = cfma(L[h], s1[h], s2[h]);
                f[h] = cfma(L[h], s2[h], f[h]);
                asm volatile("{.reg .pred p; .reg .b64 a; setp.eq.u32 p, %3, 3; mov.b64 a, {%1,%2}; @p st.relaxed.gpu.global.b64 [%0], a;}" ::"l"(cptr + h * 256),
                             "r"((__float_as_uint(f[h].x) & ~15u) | tag), "f"(f[h].y), "r"(q) : "memory");
            }
            STAMPX(2, 12);
            cf gam = lds_cf(lama + 8);
            cf st = csel(q & 2, csel(q & 1, s2[0], s1[0]), csel(q & 1, s0[0], {0.f, 0.f}));
            const cf st1 = csel(q & 2, csel(q & 1, s2[1], s1[1]), csel(q & 1, s0[1], {0.f, 0.f}));
            cptr = padd(cbase - 4 * 8192, (3 - mi) * 8192 + gl * 8);
            const int nprev = tc - 1 - mi;
            const uint8_t* hptr = padd(g_H + (size_t)(tc * 32 + wg * 16 + (cb & 6)) * 16384 + ((cb & 1) * 4 + w) * 1024, g * 64 + ((q ^ (g >> 1)) << 4));
            const uint32_t hm = 4 * (g & 1) + (q ^ (g >> 1)) == (cb & 1) * 4 + w ? ~1u : ~0u;
            float u[64];
            uint64_t fv[4] = {tag, tag, tag, tag};
            prescale<0>(u, d, gam);
            gather(fv, cptr, nprev);
#pragma unroll 1
            for (int h = 0;; h++) {
                const cf L2 = csq(L[0]), M = csq(L2);
                cf M4 = csq(csq(M));
                M4 = {__shfl_sync(~0u, M4.x, 4 * gl), __shfl_sync(~0u, M4.y, 4 * gl)};
                cf lq = cmul(gam, cmul(csel(q & 1, L[0], {1.f, 0.f}), csel(q & 2, L2, {1.f, 0.f})));
                st = cmul(gam, st);
                asm volatile("pmevent 1;" : "+f"(lq.x), "+f"(lq.y), "+f"(st.x), "+f"(st.y));
#pragma unroll 1
                for (unsigned n = 0; __any_sync(~0u, (((uint32_t)fv[0] ^ tag) | ((uint32_t)fv[1] ^ tag) | ((uint32_t)fv[2] ^ tag) | ((uint32_t)fv[3] ^ tag)) & 15u) && n < SPIN_LIMIT; n++) gather(fv, cptr, nprev);
                if (!h) STAMPX(53, 54);
                cf P = as_cf(fv[3]), pj[4];
#pragma unroll
                for (int a = 2; a >= 0; a--) P = cfma(M4, P, as_cf(fv[a]));
                cptr += 256;
                asm volatile("" : "+f"(P.x), "+f"(P.y)::"memory");
                gather(fv, cptr, h ? -1 : nprev);
#pragma unroll
                for (int j = 3; j >= 0; j--) pj[j] = {__shfl_sync(~0u, P.x, g + 8 * j), __shfl_sync(~0u, P.y, g + 8 * j)};
                st = cfma(lq, cfma(M, cfma(M, cfma(M, pj[3], pj[2]), pj[1]), pj[0]), st);
                if (!h) STAMPX(3, 13);
                uint32_t keep = sb >> 28;
                scan2(u, lam[0], st, hptr, hm, ep & ~hm, keep);
                warp_arrive(bars + B_HOWN + wg * 16 + h * 8 + keep);
                if (h) break;
                STAMPW(4, 14);
                if (wg == 1 && nu) bar_sync(9, 256);
                lds128f(lama + 128, lam[0].x, lam[0].y, gam.x, gam.y);
                st = st1;
                L[0] = L[1];
                hptr += 8 * 16384;
                prescale<1>(u, d, gam);
            }
            STAMPW(5, 15);
        }
        if (wg == 0) bar_sync(4, 128); else bar_sync(8, 128);
        if (wg == 0) {
            asm volatile("setmaxnreg.dec.sync.aligned.u32 160;");
            float y[128];
            rg = ring_at(sb, role * 66 + 32);
            STAMP(6);
            STAMP(7);
            const uint64_t dA = ring_desc(sb, 0, 512, 2), dB = ring_desc(sb, 16384, 16, 1);
            gemm2(y, rg, dA, dB, 0);
            asm volatile("setmaxnreg.inc.sync.aligned.u32 184;");
            const int lane = fresh_lane(), g = lane >> 2, q = lane & 3;
            const int pg = 2 * (g & 3) + (g >> 2);
            float* op = (float*)padd(p.out + (size_t)(tc * 128 + 64 * (w & 1) + 8 * (w >> 1)) * 2048 + 1024 + cb * 128, pg * 8192 + q * 16);
            const uint32_t xa = sb + OFF_F + (16 * (w & 1) + 8 * (w >> 1) + pg) * 128 + (((q >> 1) ^ pg) << 4) + (q & 1) * 8;
#define HALF0(k) wg_fence(); peek(k < 63 ? rg.full + SL(k + 1) * 8 : bars + B_XD, PH(k + 1)); half_step<0, k>(y, dA, dB); wg_commit(); peek_wait(k < 63 ? rg.full + SL(k + 1) * 8 : bars + B_XD, PH(k + 1), rg.n);
            HALF0(60) HALF0(61) HALF0(62) HALF0(63)
            const uint64_t dB2 = ring_desc(sb >> 1, 16384, 16, 1);
            uint32_t xa0[8], xa1[8], dd[16];
#pragma unroll
            for (int i = 0; i < 8; i++) asm volatile("ld.shared.v2.b32 {%0,%1}, [%2];" : "=r"(dd[2 * i]), "=r"(dd[2 * i + 1]) : "r"(sb + OFF_LAM + q * 8 + 32 * i) : "memory");
            load_x4<0, 0>(xa0, xa);
            wg_fence();
            half_step<64, 64 - SKEW>(y, dA, dB2);
            wg_commit();
            wg_wait<1>();
#pragma unroll
            for (int i = 0; i < 64; i++) asm volatile("" : "+f"(y[i])::"memory");
            STAMP(16);
#define MM(n) if (4 + (n) < 4 * SKEW) { wg_fence(); mma_h<64, 65 - SKEW + (n) / 4, (n) % 4>(y, dA, dB2); mma_h<64, 65 - SKEW + (n) / 4, (n) % 4 + 1>(y, dA, dB2); }
#define OUT4(R, U, X, n) out_piece<R, U>(y, dd, X[0], X[1], op); MM(n) out_piece<R, U + 1>(y, dd, X[2], X[3], op); MM(n + 2) \
                         out_piece<R, U + 2>(y, dd, X[4], X[5], op); MM(n + 4) out_piece<R, U + 3>(y, dd, X[6], X[7], op); MM(n + 6)
            load_x4<0, 4>(xa1, xa);
            OUT4(0, 0, xa0, 0)
            load_x4<1, 0>(xa0, xa);
            OUT4(0, 4, xa1, 8)
            wg_commit();
            load_x4<1, 4>(xa1, xa);
            OUT4(1, 0, xa0, 16)
            load_x4<2, 0>(xa0, xa);
            OUT4(1, 4, xa1, 16)
            STAMP(18);
            wg_wait<0>();
#pragma unroll
            for (int i = 64; i < 128; i++) asm volatile("" : "+f"(y[i])::"memory");
            STAMP(8);
            load_x4<2, 4>(xa1, xa);
            mbar_wait_fast(bars + B_XD + 8, 0);
            OUT4(2, 0, xa0, 16)
            load_x4<3, 0>(xa0, xa);
            OUT4(2, 4, xa1, 16)
            load_x4<3, 4>(xa1, xa);
            OUT4(3, 0, xa0, 16)
            OUT4(3, 4, xa1, 16)
            STAMP(9);
            return;
        }
        asm volatile("setmaxnreg.dec.sync.aligned.u32 152;");
        } else {
        if (nu) {
            constexpr int Y = YP2;
            cf T[8];
            ldtab_cf<2048>(T, TAB_T + t7 * 16);
            const uint32_t ep = get_epoch(bars);
            const int ka = pos_of(t7 >> 2);
            asm volatile("setp.eq.u32 p0, %0, 0;" ::"r"(__shfl_sync(~0u, t7, lane)));
            mbar_wait(bars + B_WSP, 0);
            mbar_wait(bars + B_FG, 0);
            uint32_t wd[4], wm[4], vo[32];
            const uint8_t* vp;
            int slot;
            const int kap0 = unit_of(role, 0, slot), al = 2 * kap0;
            const int kap1 = __shfl_sync(~0u, unit_of(role, 1, slot), 0);
            slot = __shfl_sync(~0u, slot, 0);
            cf be1 = twid(kap0 + 512 * q, 2048), be2 = csq(be1), be3 = cmul(be1, be2);
#pragma unroll
            for (int j = 0; j < 4; j++) {
                wd[j] = sb + OFF_WD + ((j + q) & 3) * WPITCH + (al & 15) + 2 * ka + 64 * q;
                wm[j] = sb + OFF_WM + (((role ? 3 : 4) - j - q) & 3) * WPITCH + (-al & 15) + 1024 - 2 * ka - 64 * q;
                wd[j] = __shfl_sync(~0u, wd[j], lane);
            }
#pragma unroll 1
            for (int u = 0; u < nu; u++) {
                const uint32_t buf = sb + OFF_P + u * 16384;
                float acc[64], za[32], zb[32], ya[32], yb[32], vv[64];
                const uint64_t dF = opaque(mkdesc(sb + OFF_F, 16, 1024, 1)), dB = opaque(mkdesc(buf, 4096, 512, 2));
                mbar_wait(bars + B_IN + u * 8, 0);
                if (!role) {
                    const uint32_t z = buf + w * 1024 + (fresh_lane() >> 2) * 128 + 64 + (fresh_lane() & 3) * 16;
#pragma unroll
                    for (int i = 0; i < 4; i++) sts128(z + i * 4096, 0, 0, 0, 0);
                    fence_async_sm();
                    bar_sync(3, 128);
                }
                STAMP3(22);
                wg_fence();
#pragma unroll
                for (int j = 0; j < 4; j++) mma128_ss<0, 0, 1>(acc, dF + j * 2, dB + j * 64, j);
                wg_commit();
                if (u) {
                    const uint32_t va = sb + OFF_P + (((uint32_t)(uintptr_t)vp - (uint32_t)(uintptr_t)g_X) >> 9 & 0x7c0) + ((uint32_t)(uintptr_t)vp & 31) + (fresh_lane() & 4) * 8;
                    bar_sync(3, 128);
#pragma unroll
                    for (int k = 0; k < 16; k++) sts64(va + ((k >> 1) & 1) * 8192 + (k >> 2) * 2048 + (k & 1) * 256, vo[2 * k], vo[2 * k + 1]);
                    fence_async_sm();
                    warp_arrive(bars + B_STG);
                    if (!role) { const uint32_t t = wm[0]; wm[0] = wm[1]; wm[1] = wm[2]; wm[2] = wm[3]; wm[3] = t; }
                }
                STAMP3(39);
                wg_wait<0>();
                pin(acc);
                STAMP3(30);
                uint32_t af[16], ag[16];
#pragma unroll
                for (int k = 0; k < 8; k++) {
                    uint32_t(&o)[16] = k < 4 ? af : ag;
                    const int c = k & 3;
#pragma unroll
                    for (int b = 0; b < 2; b++) {
                        const int i = 4 * (4 * ((k >> 2) * 2 + b) + c);
                        c2 x = mul2(c2{{acc[i], acc[i + 2]}, {acc[i + 1], acc[i + 3]}}, c2{T[2 * c], T[2 * c + 1]});
                        o[4 * c + b] = pk(x.a.x, x.a.y);
                        o[4 * c + 2 + b] = pk(x.b.x, x.b.y);
                    }
                    asm volatile("" : "+r"(o[4 * c]), "+r"(o[4 * c + 1]), "+r"(o[4 * c + 2]), "+r"(o[4 * c + 3])::"memory");
                    wg_fence();
                    mma64_rs<0>(k < 4 ? za : zb, o[4 * c], o[4 * c + 1], o[4 * c + 2], o[4 * c + 3], dF + c * 2, c);
                }
                wg_commit();
                STAMP3(31);
                mbar_wait(bars + B_WD, u & 1);
                uint32_t wr[16];
#pragma unroll
                for (int i = 0; i < 16; i++) wr[i] = lds16(wd[i >> 2] + 256 * ((i >> 1) & 1) + (i & 1) * 4 * WPITCH);
                wg_wait<0>();
                pin(za);
                pin(zb);
                pinu(af);
                pinu(ag);
                STAMP3(32);
#pragma unroll
                for (int jb = 0; jb < 4; jb++) {
                    const int i = 8 * jb;
                    c2 s0 = {{za[i], za[i + 4]}, {za[i + 1], za[i + 5]}}, s2 = {{za[i + 2], za[i + 6]}, {za[i + 3], za[i + 7]}};
                    c2 s1 = {{zb[i], zb[i + 4]}, {zb[i + 1], zb[i + 5]}}, s3 = {{zb[i + 2], zb[i + 6]}, {zb[i + 3], zb[i + 7]}};
                    s2 = mul2(s2, be1);
                    fin<Y>(s2);
                    bfly_tw<Y>(s0, s1, be2, s2, s3, be3);
                    bfly<Y>(s0, s2); bfly_mi<Y>(s1, s3);
                    c2 W[4];
#pragma unroll
                    for (int j = 0; j < 4; j++) {
                        W[j] = {{__uint_as_float(wr[4 * j] << 16), __uint_as_float(wr[4 * j + 1] << 16)}, {__uint_as_float(wr[4 * j + 2] << 16), __uint_as_float(wr[4 * j + 3] << 16)}};
                        if ((jb & 1) == 0)
                            asm volatile("@p0 ld.shared.v2.f32 {%0,%1}, [%2];" : "+f"(W[j].a.x), "+f"(W[j].a.y) : "r"(sb + OFF_WSP + u * 64 + jb * 16 + j * 8));
                    }
                    if (jb < 3) {
#pragma unroll
                        for (int k = 0; k < 16; k++) {
                            const int e = (k >> 1) & 1, pl = (k & 1) * 4 * WPITCH;
                            wr[k] = jb == 0 ? lds16(wd[k >> 2] + 512 + 256 * e + pl) : lds16(wm[k >> 2] - 512 * (jb - 1) - 256 * e + pl);
                        }
                    }
                    if (jb >= 2) {
#pragma unroll
                        for (int j = 0; j < 4; j++) { W[j].a.y = -W[j].a.y; W[j].b.y = -W[j].b.y; }
                    }
                    s0 = mul2(s0, W[0]); fin<Y>(s0);
                    s1 = mul2(s1, W[1]); fin<Y>(s1);
                    bfly_tw<Y>(s0, s2, W[2], s1, s3, W[3]);
                    bfly<Y>(s0, s1); bfly_mi<Y>(s2, s3);
                    af[4 * jb] = pk(s0.a.x, s0.b.x); af[4 * jb + 1] = pk(s3.a.x, s3.b.x); af[4 * jb + 2] = pk(s0.a.y, s0.b.y); af[4 * jb + 3] = pk(s3.a.y, s3.b.y);
                    ag[4 * jb] = pk(s1.a.x, s1.b.x); ag[4 * jb + 1] = pk(s2.a.x, s2.b.x); ag[4 * jb + 2] = pk(s1.a.y, s1.b.y); ag[4 * jb + 3] = pk(s2.a.y, s2.b.y);
                }
                pinu(af);
                pinu(ag);
                warp_arrive(bars + B_WFREE);
                wg_fence();
#pragma unroll
                for (int j = 0; j < 4; j++) mma64_rs<1>(ya, af[4 * j], af[4 * j + 1], af[4 * j + 2], af[4 * j + 3], dF + j * 128, j);
                wg_commit();
#pragma unroll
                for (int j = 0; j < 4; j++) mma64_rs<1>(yb, ag[4 * j], ag[4 * j + 1], ag[4 * j + 2], ag[4 * j + 3], dF + j * 128, j);
                wg_commit();
                STAMP3(33);
                {
                    const uint32_t a0 = buf + (mi & 1) * 4096 + (16 * w + 8 * (mi >> 1) + gl) * 64 + ((gl >> 1) << 4);
#pragma unroll
                    for (int h = 0; h < 2; h++) {
                        if (h == 0) { wg_wait<1>(); pin(ya); pinu(af); STAMP3(34); } else { wg_wait<0>(); pin(yb); pinu(ag); }
                        const float(&yy)[32] = h ? yb : ya;
#pragma unroll
                        for (int c = 0; c < 4; c++) {
                            const int i = 8 * ((c + 2 * h) & 3), k = 8 * ((c + 2 * h + 1) & 3) + 2;
                            c2 x = {cmulc({yy[i], yy[i + 1]}, T[2 * c]), cmulc({yy[k], yy[k + 1]}, T[2 * c])};
                            fin<1>(x);
                            c2 y = {cmulc({yy[i + 4], yy[i + 5]}, T[2 * c + 1]), cmulc({yy[k + 4], yy[k + 5]}, T[2 * c + 1])};
                            fin<1>(y);
                            stsm4((a0 ^ (c << 4)) + h * 8192, pk(x.a.x, y.a.x), pk(x.b.x, y.b.x), pk(x.a.y, y.a.y), pk(x.b.y, y.b.y));
                        }
                    }
                }
                STAMP3(38);
                fence_async_sm();
                bar_sync(3, 128);
                wg_fence();
#pragma unroll
                for (int j = 0; j < 4; j++) mma128_ss<0, 1, 1>(vv, dF + j * 128, dB + j * 64, j);
                wg_commit();
                STAMP3(35);
                if (u && !spare) bar_arrive(9, 256);
                const int lane = fresh_lane(), g = lane >> 2, q = lane & 3;
                vp = padd(g_X + (4 << 20) + w * (8 * 32768) + (role ? u : 1) * 16384 + slot * 64,
                                         (g >> 1) * 32768 + (role ? g & 1 : u) * 32 + (((q ^ (slot >> 1)) & 1) << 4) + (q >> 1) * 8);
                const uint32_t tmask = (((g & 1) == ((slot >> 3) & 1) || !role) && q == ((slot >> 1) & 2)) ? ~1u : ~0u, tbit = (ep ^ (role + u ? 0 : g)) & ~tmask;
                be1 = twid(kap1 + 512 * q, 2048); be2 = csq(be1); be3 = cmul(be1, be2);
                asm volatile("pmevent 1;" : "+f"(be1.x), "+f"(be1.y), "+f"(be2.x), "+f"(be2.y), "+f"(be3.x), "+f"(be3.y), "+l"(vp)::"memory");
                wg_wait<0>();
                pin(vv);
                STAMP3(36);
#pragma unroll
                for (int k = 0; k < 16; k++) {
                    const int i = 8 * (k >> 1) + 2 * (k & 1);
                    vo[2 * k] = (pk(vv[i], vv[i + 1]) & tmask) | tbit;
                    vo[2 * k + 1] = pk(vv[i + 4], vv[i + 5]);
                }
                pinu(vo);
            }
            if (!role) mbar_wait(bars + B_IN + 16, 0);
            warp_arrive(bars + B_STG);
            const bool odd = fresh_lane() & 4;
            store_v<0, 4>(vo, vp, role || !odd);
            asm volatile("@p0 red.relaxed.gpu.global.add.u32 [%0], 1;" ::"l"(g_cnt + 32 + nu * 32) : "memory");
            store_v<4, 16>(vo, vp, role || odd);
        }
        if (spare) return;
        }
        {
            constexpr int Y = YP3;
            uint32_t sp[8];
            cf tw[8];
            ldtab<2, 2048>(sp, TAB_SP + fb * 4096 + t7 * 16);
            ldtab_cf<16>(tw, TAB_TW3 + fb * 2048 + (t7 >> 2) * 64);
            const uint64_t dF = opaque(mkdesc(sb + OFF_F, 16, 1024, 1)), dB = opaque(mkdesc(sb + OFF_P + hf * 8192, 1024, 256, 3));
            const uint8_t* op = padd(p.out + (1024 + fb) * 2048 + fcb * 32 + hf * 16, (t7 >> 2) * 32768 + (q >> 1) * 16 + (q & 1) * 32);
            float acc[64], out[64];
            mbar_wait(bars + B_IN + 24, 0);
            mbar_wait(bars + B_FG, 1);
            STAMP(25);
            pinu(sp);
            wg_fence();
#pragma unroll
            for (int j = 0; j < 4; j++) {
                const uint64_t db = dB + (j >> 1) * 1024 + (j & 1) * 32;
                mma112_ss(acc, dF + j * 2, db + 64, j);
                if (j & 1) mma16_rs(acc, 0u, sp[2 * j], 0u, sp[2 * j + 1], db, 1);
                else mma16_rs(acc, sp[2 * j], 0u, sp[2 * j + 1], 0u, db, j);
            }
            wg_commit();
            wg_wait<0>();
            pin(acc);
            pinu(sp);
            warp_arrive(bars + B_P3M);
            if (!hf) bar_sync(5, 256);
#pragma unroll
            for (int cl = 0; cl < 2; cl++) {
                c2 z[8];
#pragma unroll
                for (int n = 0; n < 8; n++) {
                    const int i = 4 * (2 * n + cl);
                    z[n] = {{acc[i], acc[i + 2]}, {acc[i + 1], acc[i + 3]}};
                }
                z[0] = {{z[0].a.x + z[0].a.y, z[0].a.x - z[0].a.y}, {z[0].b.x + z[0].b.y, z[0].b.x - z[0].b.y}};
                z[4] = mul2(z[4], tw[4]);
                fin<Y>(z[0], z[4]);
#pragma unroll
                for (int n = 1; n < 4; n++) {
                    const cf iw = n == 1 ? cf{0.38268343236508977f, 0.92387953251128674f}
                                         : (n == 2 ? cf{0.70710678118654752f, 0.70710678118654752f} : cf{0.92387953251128674f, 0.38268343236508977f});
                    c2 y = mul2(z[n], tw[n]);
                    fin<Y>(y);
                    const cf t = {tw[8 - n].x, -tw[8 - n].y};
                    c2 E = fma2(c2{{z[8 - n].a.x, -z[8 - n].a.y}, {z[8 - n].b.x, -z[8 - n].b.y}}, t, y);
                    fin<Y>(E);
                    z[n] = fma2(twm2(y, E), iw, E);
                    fin<Y>(z[n]);
                    z[8 - n] = {{fmaf(2.f, E.a.x, -z[n].a.x), fmaf(-2.f, E.a.y, z[n].a.y)}, {fmaf(2.f, E.b.x, -z[n].b.x), fmaf(-2.f, E.b.y, z[n].b.y)}};
                }
                dft8<false, Y>(z, tw);
#pragma unroll
                for (int m = 0; m < 8; m++) {
                    out[8 * m + 2 * cl] = z[m].a.x; out[8 * m + 2 * cl + 1] = z[m].b.x;
                    out[8 * m + 4 + 2 * cl] = z[m].a.y; out[8 * m + 5 + 2 * cl] = z[m].b.y;
                }
            }
            pin(out);
            if (hf) bar_arrive(5, 256);
            if (hf) STAMP(26);
#pragma unroll
            for (int m = 0; m < 16; m++) {
                asm volatile("st.global.v4.f32 [%0], {%1,%2,%3,%4};" ::"l"(op + (m - 8) * (1 << 20)), "f"(out[4 * m]), "f"(out[4 * m + 1]), "f"(out[4 * m + 2]), "f"(out[4 * m + 3]) : "memory");
                if (PACE_O && m < 15 && m % PACE_ON == PACE_ON - 1)
                    asm volatile("{.reg .pred p; mbarrier.test_wait.parity.shared::cta.b64 p, [%0], 0; @!p nanosleep.u32 %1;}" ::"r"(bars + B_DONE), "n"(PACE_O) : "memory");
            }
            STAMP(27);
        }
    }
}

typedef CUresult (*EncodeFn)(CUtensorMap*, CUtensorMapDataType, cuuint32_t, void*, const cuuint64_t*, const cuuint64_t*, const cuuint32_t*,
                             const cuuint32_t*, CUtensorMapInterleave, CUtensorMapSwizzle, CUtensorMapL2promotion, CUtensorMapFloatOOBfill);

static CUtensorMap make_map(EncodeFn enc, const void* ptr, int rank, const cuuint64_t* dims, const cuuint64_t* strides, const cuuint32_t* box,
                            CUtensorMapSwizzle swz, CUtensorMapL2promotion promo, CUtensorMapDataType dt = CU_TENSOR_MAP_DATA_TYPE_BFLOAT16) {
    CUtensorMap m;
    const cuuint32_t es[5] = {1, 1, 1, 1, 1};
    enc(&m, dt, rank, const_cast<void*>(ptr), dims, strides, box, es, CU_TENSOR_MAP_INTERLEAVE_NONE, swz, promo,
        CU_TENSOR_MAP_FLOAT_OOB_FILL_NONE);
    return m;
}

extern "C" void kernel_launch(void* const* d_in, const int* in_sizes, int n_in, void* d_out, int out_size) {
    void* fn = nullptr;
    cudaDriverEntryPointQueryResult qr;
    cudaGetDriverEntryPoint("cuTensorMapEncodeTiled", &fn, cudaEnableDefault, &qr);
    EncodeFn enc = (EncodeFn)fn;
    void* pX;
    cudaGetSymbolAddress(&pX, g_X);
    const CUtensorMapL2promotion P256 = CU_TENSOR_MAP_L2_PROMOTION_L2_256B, P0 = CU_TENSOR_MAP_L2_PROMOTION_NONE;

    const cuuint64_t dX[5] = {1024, 2, 4, 16, 16}, sX[4] = {2048, 32 * 2048, 2 * 2048, 128 * 2048};
    const cuuint32_t bX[5] = {64, 2, 4, 16, 1};
    CUtensorMap tmX = make_map(enc, d_in[3], 5, dX, sX, bX, CU_TENSOR_MAP_SWIZZLE_128B, P256);
    const cuuint64_t dXd[4] = {64, 2048, 2, 16}, sXd[3] = {2048, 64 * 2048, 128};
    const cuuint32_t bXd[4] = {64, 16, 2, 2};
    CUtensorMap tmXd = make_map(enc, d_in[3], 4, dXd, sXd, bXd, CU_TENSOR_MAP_SWIZZLE_128B, P256);
    const cuuint64_t dB[4] = {1024, 8, 4, 32}, sB[3] = {2048, 256 * 2048, 8 * 2048};
    const cuuint32_t bB4[4] = {64, 8, 2, 4};
    CUtensorMap tmBre = make_map(enc, d_in[6], 4, dB, sB, bB4, CU_TENSOR_MAP_SWIZZLE_128B, P256);
    CUtensorMap tmBim = make_map(enc, d_in[7], 4, dB, sB, bB4, CU_TENSOR_MAP_SWIZZLE_128B, P256);
    const cuuint64_t dC[5] = {1024, 2, 4, 2, 64}, sC[4] = {2048, 4 * 2048, 2 * 2048, 16 * 2048};
    const cuuint32_t bC[5] = {64, 2, 4, 2, 4};
    CUtensorMap tmCre = make_map(enc, d_in[8], 5, dC, sC, bC, CU_TENSOR_MAP_SWIZZLE_128B, P256);
    CUtensorMap tmCim = make_map(enc, d_in[9], 5, dC, sC, bC, CU_TENSOR_MAP_SWIZZLE_128B, P256);

    const cuuint64_t dU[2] = {8192, 256}, sU[1] = {16384};
    const cuuint32_t bU[2] = {64, 64};
    CUtensorMap tmUst = make_map(enc, pX, 2, dU, sU, bU, CU_TENSOR_MAP_SWIZZLE_128B, P0);
    const cuuint64_t dV[2] = {16384, 128}, sV[1] = {32768};
    const cuuint32_t bV[2] = {32, 128};
    CUtensorMap tmVst = make_map(enc, (uint8_t*)pX + (4 << 20), 2, dV, sV, bV, CU_TENSOR_MAP_SWIZZLE_NONE, P0);
    const cuuint64_t dF[2] = {512 * 1026 / 8, 4}, sF[1] = {512 * 1026};
    const cuuint32_t bF[2] = {WPITCH / 8, 4};
    CUtensorMap tmWr = make_map(enc, d_in[1], 2, dF, sF, bF, CU_TENSOR_MAP_SWIZZLE_NONE, P0, CU_TENSOR_MAP_DATA_TYPE_UINT64);
    CUtensorMap tmWi = make_map(enc, d_in[2], 2, dF, sF, bF, CU_TENSOR_MAP_SWIZZLE_NONE, P0, CU_TENSOR_MAP_DATA_TYPE_UINT64);

    const cuuint64_t dA[3] = {1024, 64, 32}, sA[2] = {32 * 2048, 2048};
    const cuuint32_t bA[3] = {32, 64, 1};
    CUtensorMap tmXa = make_map(enc, d_in[0], 3, dA, sA, bA, CU_TENSOR_MAP_SWIZZLE_64B, CU_TENSOR_MAP_L2_PROMOTION_L2_128B);

    Params p;
    p.wr = (const __nv_bfloat16*)d_in[1];
    p.wi = (const __nv_bfloat16*)d_in[2];
    p.lre = (const __nv_bfloat16*)d_in[4];
    p.lim = (const __nv_bfloat16*)d_in[5];
    p.ldt = (const __nv_bfloat16*)d_in[10];
    p.dsk = (const __nv_bfloat16*)d_in[11];
    p.out = (float*)d_out;
    int dev = 0, sms = 0;
    cudaGetDevice(&dev);
    cudaDeviceGetAttribute(&sms, cudaDevAttrMultiProcessorCount, dev);
    auto kernel = sms == 132 ? fused_kernel<true> : fused_kernel<false>;
    cudaFuncSetAttribute(kernel, cudaFuncAttributeMaxDynamicSharedMemorySize, SMEM_BYTES);
    kernel<<<132, 512, SMEM_BYTES>>>(tmX, tmBre, tmBim, tmCre, tmCim, tmXd, tmUst, tmVst, tmWr, tmWi, tmXa, p);
}
```

```cpp
#include <cuda_runtime.h>
#include <cuda.h>
#include <cuda_bf16.h>
#include <stdint.h>

#define NST 5
#define WPITCH 1056
#define OFF_P (NST * 32768)
#define OFF_F (OFF_P + 32768)
#define OFF_WD (OFF_F + 8192)
#define OFF_WM (OFF_WD + 8 * WPITCH)
#define OFF_BAR (OFF_F + 32768)
#define OFF_LAM (OFF_BAR + 432)
#define OFF_WSP (OFF_LAM + 2048)
#define OFF_PROF (OFF_WSP + 128)
#define SMEM_BYTES OFF_PROF
#define B_FULL 0
#define B_HL 40
#define B_EP 120
#define B_HR 128
#define B_XD 144
#define B_FG 160
#define B_WSP 168
#define B_WD 176
#define B_DONE 184
#define B_LD 192
#define B_RAW 200
#define B_LAM 208
#define B_IN 216
#define B_XIN 248
#define B_EMPTY 256
#define B_STG 320
#define B_WFREE 328
#define B_HOWN 336
#define B_STGU 368
#define B_P3M 384
#define B_EPOCH 416

#define XA_PACE 200
#define PACE_O 200
#define PACE_ON 2
#define TAB_T0 500
#define LAM_T0 1000
#define UH0 1
#define UH1 0
#define XA_N0 2
#define PACE_X 200
#define SKEW 4
#define SPIN_LIMIT (1u << 15)

__device__ __align__(1024) uint8_t g_X[8 << 20];
__device__ __align__(1024) uint8_t g_H[8 << 20];
__device__ __align__(1024) uint4 g_carry[16 * 512];
__device__ __align__(128) unsigned g_cnt[128];
__device__ __align__(128) unsigned g_epoch[132 * 8];

#define STAMP(i) do { } while (0)
#define STAMPO(i, o) do { } while (0)
#define STAMPW(a, b) do { } while (0)
#define STAMPX(a, b) do { } while (0)
#define STAMP5(i) do { } while (0)
#define STAMP3(i) do { } while (0)

#define TAB_FG 0
#define TAB_G 8192
#define TAB_F1 40960
#define TAB_T 49152
#define TAB_SP 57344
#define TAB_TW1 73728
#define TAB_TW3 75776
#define TAB_PC 83968
__device__ __align__(1024) const uint32_t g_tab[21248] = {
0x80003d80,0x80003d80,0x80003d80,0x80003d80,0x80003d80,0x80003d80,0x80003d80,0x80003d80,0x80003d80,0x80003d80,0x80003d80,0x80003d80,0x80003d80,0x80003d80,0x80003d80,0x80003d80,
0x80003d80,0x80003d80,0x80003d80,0x80003d80,0x80003d80,0x80003d80,0x80003d80,0x80003d80,0x80003d80,0x80003d80,0x80003d80,0x80003d80,0x80003d80,0x80003d80,0x80003d80,0x80003d80,
0x3d353d35,0x3d35bd35,0xbd35bd35,0xbd353d35,0x80003d80,0x3d800000,0x8000bd80,0xbd800000,0x3d353d35,0x3d35bd35,0xbd35bd35,0xbd353d35,0x80003d80,0x3d800000,0x8000bd80,0xbd800000,
0x3d353d35,0x3d35bd35,0xbd35bd35,0xbd353d35,0x80003d80,0x3d800000,0x8000bd80,0xbd800000,0x3d353d35,0x3d35bd35,0xbd35bd35,0xbd353d35,0x80003d80,0x3d800000,0x8000bd80,0xbd800000,
0x3d800000,0x3d6dbcc4,0x3d35bd35,0x3cc4bd6d,0x3d7bbc48,0x3d55bd0e,0x3d0ebd55,0x3c48bd7b,0x80003d80,0x3cc43d6d,0x3d353d35,0x3d6d3cc4,0x3c483d7b,0x3d0e3d55,0x3d553d0e,0x3d7b3c48,
0xbd800000,0xbd6d3cc4,0xbd353d35,0xbcc43d6d,0xbd7b3c48,0xbd553d0e,0xbd0e3d55,0xbc483d7b,0x8000bd80,0xbcc4bd6d,0xbd35bd35,0xbd6dbcc4,0xbc48bd7b,0xbd0ebd55,0xbd55bd0e,0xbd7bbc48,
0x3d0ebd55,0xbd7bbc48,0x3c483d7b,0x3d55bd0e,0x3d800000,0xbcc4bd6d,0xbd353d35,0x3d6d3cc4,0x3d553d0e,0x3c48bd7b,0xbd7b3c48,0x3d0e3d55,0x80003d80,0x3d6dbcc4,0xbd35bd35,0xbcc43d6d,
0xbd0e3d55,0x3d7b3c48,0xbc48bd7b,0xbd553d0e,0xbd800000,0x3cc43d6d,0x3d35bd35,0xbd6dbcc4,0xbd55bd0e,0xbc483d7b,0x3d7bbc48,0xbd0ebd55,0x8000bd80,0xbd6d3cc4,0x3d353d35,0x3cc4bd6d,
0x80003d80,0x3d353d35,0x3d800000,0x3d35bd35,0x3cc43d6d,0x3d6d3cc4,0x3d6dbcc4,0x3cc4bd6d,0x8000bd80,0xbd35bd35,0xbd800000,0xbd353d35,0xbcc4bd6d,0xbd6dbcc4,0xbd6d3cc4,0xbcc43d6d,
0x80003d80,0x3d353d35,0x3d800000,0x3d35bd35,0x3cc43d6d,0x3d6d3cc4,0x3d6dbcc4,0x3cc4bd6d,0x8000bd80,0xbd35bd35,0xbd800000,0xbd353d35,0xbcc4bd6d,0xbd6dbcc4,0xbd6d3cc4,0xbcc43d6d,
0x3d6d3cc4,0xbcc4bd6d,0xbcc43d6d,0x3d6dbcc4,0x80003d80,0x3d35bd35,0xbd800000,0x3d353d35,0xbd6dbcc4,0x3cc43d6d,0x3cc4bd6d,0xbd6d3cc4,0x8000bd80,0xbd353d35,0x3d800000,0xbd35bd35,
0x3d6d3cc4,0xbcc4bd6d,0xbcc43d6d,0x3d6dbcc4,0x80003d80,0x3d35bd35,0xbd800000,0x3d353d35,0xbd6dbcc4,0x3cc43d6d,0x3cc4bd6d,0xbd6d3cc4,0x8000bd80,0xbd353d35,0x3d800000,0xbd35bd35,
0x3d800000,0x3cc4bd6d,0xbd35bd35,0xbd6d3cc4,0x3d55bd0e,0xbc48bd7b,0xbd7bbc48,0xbd0e3d55,0x8000bd80,0xbd6dbcc4,0xbd353d35,0x3cc43d6d,0xbd0ebd55,0xbd7b3c48,0xbc483d7b,0x3d553d0e,
0xbd800000,0xbcc43d6d,0x3d353d35,0x3d6dbcc4,0xbd553d0e,0x3c483d7b,0x3d7b3c48,0x3d0ebd55,0x80003d80,0x3d6d3cc4,0x3d35bd35,0xbcc4bd6d,0x3d0e3d55,0x3d7bbc48,0x3c48bd7b,0xbd55bd0e,
0x3c48bd7b,0xbd0e3d55,0x3d55bd0e,0xbd7b3c48,0x3d800000,0xbd6dbcc4,0x3d353d35,0xbcc4bd6d,0xbd7bbc48,0x3d553d0e,0xbd0ebd55,0x3c483d7b,0x8000bd80,0xbcc43d6d,0x3d35bd35,0xbd6d3cc4,
0xbc483d7b,0x3d0ebd55,0xbd553d0e,0x3d7bbc48,0xbd800000,0x3d6d3cc4,0xbd35bd35,0x3cc43d6d,0x3d7b3c48,0xbd55bd0e,0x3d0e3d55,0xbc48bd7b,0x80003d80,0x3cc4bd6d,0xbd353d35,0x3d6dbcc4,
0x3d800000,0x3d800000,0x3d800000,0x3d800000,0x3d800000,0x3d800000,0x3d800000,0x3d800000,0x3d800000,0x3d800000,0x3d800000,0x3d800000,0x3d800000,0x3d800000,0x3d800000,0x3d800000,
0x3d800000,0x3d800000,0x3d800000,0x3d800000,0x3d800000,0x3d800000,0x3d800000,0x3d800000,0x3d800000,0x3d800000,0x3d800000,0x3d800000,0x3d800000,0x3d800000,0x3d800000,0x3d800000,
0x3d35bd35,0xbd35bd35,0xbd353d35,0x3d353d35,0x3d800000,0xbd80,0xbd800000,0x3d80,0x3d35bd35,0xbd35bd35,0xbd353d35,0x3d353d35,0x3d800000,0xbd80,0xbd800000,0x3d80,
0x3d35bd35,0xbd35bd35,0xbd353d35,0x3d353d35,0x3d800000,0xbd80,0xbd800000,0x3d80,0x3d35bd35,0xbd35bd35,0xbd353d35,0x3d353d35,0x3d800000,0xbd80,0xbd800000,0x3d80,
0xbd80,0xbcc4bd6d,0xbd35bd35,0xbd6dbcc4,0xbc48bd7b,0xbd0ebd55,0xbd55bd0e,0xbd7bbc48,0x3d800000,0x3d6dbcc4,0x3d35bd35,0x3cc4bd6d,0x3d7bbc48,0x3d55bd0e,0x3d0ebd55,0x3c48bd7b,
0x3d80,0x3cc43d6d,0x3d353d35,0x3d6d3cc4,0x3c483d7b,0x3d0e3d55,0x3d553d0e,0x3d7b3c48,0xbd800000,0xbd6d3cc4,0xbd353d35,0xbcc43d6d,0xbd7b3c48,0xbd553d0e,0xbd0e3d55,0xbc483d7b,
0xbd55bd0e,0xbc483d7b,0x3d7bbc48,0xbd0ebd55,0xbd80,0xbd6d3cc4,0x3d353d35,0x3cc4bd6d,0x3d0ebd55,0xbd7bbc48,0x3c483d7b,0x3d55bd0e,0x3d800000,0xbcc4bd6d,0xbd353d35,0x3d6d3cc4,
0x3d553d0e,0x3c48bd7b,0xbd7b3c48,0x3d0e3d55,0x3d80,0x3d6dbcc4,0xbd35bd35,0xbcc43d6d,0xbd0e3d55,0x3d7b3c48,0xbc48bd7b,0xbd553d0e,0xbd800000,0x3cc43d6d,0x3d35bd35,0xbd6dbcc4,
0x3d800000,0x3d35bd35,0xbd80,0xbd35bd35,0x3d6dbcc4,0x3cc4bd6d,0xbcc4bd6d,0xbd6dbcc4,0xbd800000,0xbd353d35,0x3d80,0x3d353d35,0xbd6d3cc4,0xbcc43d6d,0x3cc43d6d,0x3d6d3cc4,
0x3d800000,0x3d35bd35,0xbd80,0xbd35bd35,0x3d6dbcc4,0x3cc4bd6d,0xbcc4bd6d,0xbd6dbcc4,0xbd800000,0xbd353d35,0x3d80,0x3d353d35,0xbd6d3cc4,0xbcc43d6d,0x3cc43d6d,0x3d6d3cc4,
0x3cc4bd6d,0xbd6d3cc4,0x3d6d3cc4,0xbcc4bd6d,0x3d800000,0xbd35bd35,0x3d80,0x3d35bd35,0xbcc43d6d,0x3d6dbcc4,0xbd6dbcc4,0x3cc43d6d,0xbd800000,0x3d353d35,0xbd80,0xbd353d35,
0x3cc4bd6d,0xbd6d3cc4,0x3d6d3cc4,0xbcc4bd6d,0x3d800000,0xbd35bd35,0x3d80,0x3d35bd35,0xbcc43d6d,0x3d6dbcc4,0xbd6dbcc4,0x3cc43d6d,0xbd800000,0x3d353d35,0xbd80,0xbd353d35,
0xbd80,0xbd6dbcc4,0xbd353d35,0x3cc43d6d,0xbd0ebd55,0xbd7b3c48,0xbc483d7b,0x3d553d0e,0xbd800000,0xbcc43d6d,0x3d353d35,0x3d6dbcc4,0xbd553d0e,0x3c483d7b,0x3d7b3c48,0x3d0ebd55,
0x3d80,0x3d6d3cc4,0x3d35bd35,0xbcc4bd6d,0x3d0e3d55,0x3d7bbc48,0x3c48bd7b,0xbd55bd0e,0x3d800000,0x3cc4bd6d,0xbd35bd35,0xbd6d3cc4,0x3d55bd0e,0xbc48bd7b,0xbd7bbc48,0xbd0e3d55,
0xbd7bbc48,0x3d553d0e,0xbd0ebd55,0x3c483d7b,0xbd80,0xbcc43d6d,0x3d35bd35,0xbd6d3cc4,0xbc483d7b,0x3d0ebd55,0xbd553d0e,0x3d7bbc48,0xbd800000,0x3d6d3cc4,0xbd35bd35,0x3cc43d6d,
0x3d7b3c48,0xbd55bd0e,0x3d0e3d55,0xbc48bd7b,0x3d80,0x3cc4bd6d,0xbd353d35,0x3d6dbcc4,0x3c48bd7b,0xbd0e3d55,0x3d55bd0e,0xbd7b3c48,0x3d800000,0xbd6dbcc4,0x3d353d35,0xbcc4bd6d,
0x80003d80,0x8000bd80,0x80003d80,0x8000bd80,0x3d800000,0xbd800000,0x3d800000,0xbd800000,0x80003d80,0x8000bd80,0x80003d80,0x8000bd80,0x3d800000,0xbd800000,0x3d800000,0xbd800000,
0x80003d80,0x8000bd80,0x80003d80,0x8000bd80,0x3d800000,0xbd800000,0x3d800000,0xbd800000,0x80003d80,0x8000bd80,0x80003d80,0x8000bd80,0x3d800000,0xbd800000,0x3d800000,0xbd800000,
0x3d35bd35,0x3d353d35,0xbd353d35,0xbd35bd35,0x80003d80,0xbd800000,0x8000bd80,0x3d800000,0x3d35bd35,0x3d353d35,0xbd353d35,0xbd35bd35,0x80003d80,0xbd800000,0x8000bd80,0x3d800000,
0x3d35bd35,0x3d353d35,0xbd353d35,0xbd35bd35,0x80003d80,0xbd800000,0x8000bd80,0x3d800000,0x3d35bd35,0x3d353d35,0xbd353d35,0xbd35bd35,0x80003d80,0xbd800000,0x8000bd80,0x3d800000,
0x3d800000,0xbd6d3cc4,0x3d35bd35,0xbcc43d6d,0xbc48bd7b,0x3d0e3d55,0xbd55bd0e,0x3d7b3c48,0x80003d80,0xbcc4bd6d,0x3d353d35,0xbd6dbcc4,0x3d7bbc48,0xbd553d0e,0x3d0ebd55,0xbc483d7b,
0xbd800000,0x3d6dbcc4,0xbd353d35,0x3cc4bd6d,0x3c483d7b,0xbd0ebd55,0x3d553d0e,0xbd7bbc48,0x8000bd80,0x3cc43d6d,0xbd35bd35,0x3d6d3cc4,0xbd7b3c48,0x3d55bd0e,0xbd0e3d55,0x3c48bd7b,
0xbd55bd0e,0x3c48bd7b,0x3d7bbc48,0x3d0e3d55,0x3d800000,0x3cc43d6d,0xbd353d35,0xbd6dbcc4,0x3d0ebd55,0x3d7b3c48,0x3c483d7b,0xbd553d0e,0x80003d80,0xbd6d3cc4,0xbd35bd35,0x3cc4bd6d,
0x3d553d0e,0xbc483d7b,0xbd7b3c48,0xbd0ebd55,0xbd800000,0xbcc4bd6d,0x3d35bd35,0x3d6d3cc4,0xbd0e3d55,0xbd7bbc48,0xbc48bd7b,0x3d55bd0e,0x8000bd80,0x3d6dbcc4,0x3d353d35,0xbcc43d6d,
0x80003d80,0xbd35bd35,0x3d800000,0xbd353d35,0x3d6dbcc4,0xbcc43d6d,0xbcc4bd6d,0x3d6d3cc4,0x8000bd80,0x3d353d35,0xbd800000,0x3d35bd35,0xbd6d3cc4,0x3cc4bd6d,0x3cc43d6d,0xbd6dbcc4,
0x80003d80,0xbd35bd35,0x3d800000,0xbd353d35,0x3d6dbcc4,0xbcc43d6d,0xbcc4bd6d,0x3d6d3cc4,0x8000bd80,0x3d353d35,0xbd800000,0x3d35bd35,0xbd6d3cc4,0x3cc4bd6d,0x3cc43d6d,0xbd6dbcc4,
0x3cc4bd6d,0x3d6dbcc4,0x3d6d3cc4,0x3cc43d6d,0x80003d80,0xbd353d35,0xbd800000,0xbd35bd35,0xbcc43d6d,0xbd6d3cc4,0xbd6dbcc4,0xbcc4bd6d,0x8000bd80,0x3d35bd35,0x3d800000,0x3d353d35,
0x3cc4bd6d,0x3d6dbcc4,0x3d6d3cc4,0x3cc43d6d,0x80003d80,0xbd353d35,0xbd800000,0xbd35bd35,0xbcc43d6d,0xbd6d3cc4,0xbd6dbcc4,0xbcc4bd6d,0x8000bd80,0x3d35bd35,0x3d800000,0x3d353d35,
0x3d800000,0xbcc43d6d,0xbd35bd35,0x3d6dbcc4,0xbd0ebd55,0x3d7bbc48,0xbc483d7b,0xbd55bd0e,0x8000bd80,0x3d6d3cc4,0xbd353d35,0xbcc4bd6d,0xbd553d0e,0xbc48bd7b,0x3d7b3c48,0xbd0e3d55,
0xbd800000,0x3cc4bd6d,0x3d353d35,0xbd6d3cc4,0x3d0e3d55,0xbd7b3c48,0x3c48bd7b,0x3d553d0e,0x80003d80,0xbd6dbcc4,0x3d35bd35,0x3cc43d6d,0x3d55bd0e,0x3c483d7b,0xbd7bbc48,0x3d0ebd55,
0xbd7bbc48,0xbd55bd0e,0xbd0ebd55,0xbc48bd7b,0x3d800000,0x3d6d3cc4,0x3d353d35,0x3cc43d6d,0xbc483d7b,0xbd0e3d55,0xbd553d0e,0xbd7b3c48,0x8000bd80,0x3cc4bd6d,0x3d35bd35,0x3d6dbcc4,
0x3d7b3c48,0x3d553d0e,0x3d0e3d55,0x3c483d7b,0xbd800000,0xbd6dbcc4,0xbd35bd35,0xbcc4bd6d,0x3c48bd7b,0x3d0ebd55,0x3d55bd0e,0x3d7bbc48,0x80003d80,0xbcc43d6d,0xbd353d35,0xbd6d3cc4,
0x3d800000,0xbd800000,0x3d800000,0xbd800000,0xbd80,0x3d80,0xbd80,0x3d80,0x3d800000,0xbd800000,0x3d800000,0xbd800000,0xbd80,0x3d80,0xbd80,0x3d80,
0x3d800000,0xbd800000,0x3d800000,0xbd800000,0xbd80,0x3d80,0xbd80,0x3d80,0x3d800000,0xbd800000,0x3d800000,0xbd800000,0xbd80,0x3d80,0xbd80,0x3d80,
0xbd35bd35,0x3d35bd35,0x3d353d35,0xbd353d35,0x3d800000,0x3d80,0xbd800000,0xbd80,0xbd35bd35,0x3d35bd35,0x3d353d35,0xbd353d35,0x3d800000,0x3d80,0xbd800000,0xbd80,
0xbd35bd35,0x3d35bd35,0x3d353d35,0xbd353d35,0x3d800000,0x3d80,0xbd800000,0xbd80,0xbd35bd35,0x3d35bd35,0x3d353d35,0xbd353d35,0x3d800000,0x3d80,0xbd800000,0xbd80,
0xbd80,0x3cc43d6d,0xbd35bd35,0x3d6d3cc4,0xbd7b3c48,0x3d55bd0e,0xbd0e3d55,0x3c48bd7b,0x3d800000,0xbd6d3cc4,0x3d35bd35,0xbcc43d6d,0xbc48bd7b,0x3d0e3d55,0xbd55bd0e,0x3d7b3c48,
0x3d80,0xbcc4bd6d,0x3d353d35,0xbd6dbcc4,0x3d7bbc48,0xbd553d0e,0x3d0ebd55,0xbc483d7b,0xbd800000,0x3d6dbcc4,0xbd353d35,0x3cc4bd6d,0x3c483d7b,0xbd0ebd55,0x3d553d0e,0xbd7bbc48,
0xbd0e3d55,0xbd7bbc48,0xbc48bd7b,0x3d55bd0e,0xbd80,0x3d6dbcc4,0x3d353d35,0xbcc43d6d,0xbd55bd0e,0x3c48bd7b,0x3d7bbc48,0x3d0e3d55,0x3d800000,0x3cc43d6d,0xbd353d35,0xbd6dbcc4,
0x3d0ebd55,0x3d7b3c48,0x3c483d7b,0xbd553d0e,0x3d80,0xbd6d3cc4,0xbd35bd35,0x3cc4bd6d,0x3d553d0e,0xbc483d7b,0xbd7b3c48,0xbd0ebd55,0xbd800000,0xbcc4bd6d,0x3d35bd35,0x3d6d3cc4,
0x3d800000,0xbd353d35,0xbd80,0x3d353d35,0xbcc4bd6d,0x3d6d3cc4,0xbd6d3cc4,0x3cc4bd6d,0xbd800000,0x3d35bd35,0x3d80,0xbd35bd35,0x3cc43d6d,0xbd6dbcc4,0x3d6dbcc4,0xbcc43d6d,
0x3d800000,0xbd353d35,0xbd80,0x3d353d35,0xbcc4bd6d,0x3d6d3cc4,0xbd6d3cc4,0x3cc4bd6d,0xbd800000,0x3d35bd35,0x3d80,0xbd35bd35,0x3cc43d6d,0xbd6dbcc4,0x3d6dbcc4,0xbcc43d6d,
0xbd6dbcc4,0xbcc4bd6d,0x3cc4bd6d,0x3d6dbcc4,0x3d800000,0x3d353d35,0x3d80,0xbd353d35,0x3d6d3cc4,0x3cc43d6d,0xbcc43d6d,0xbd6d3cc4,0xbd800000,0xbd35bd35,0xbd80,0x3d35bd35,
0xbd6dbcc4,0xbcc4bd6d,0x3cc4bd6d,0x3d6dbcc4,0x3d800000,0x3d353d35,0x3d80,0xbd353d35,0x3d6d3cc4,0x3cc43d6d,0xbcc43d6d,0xbd6d3cc4,0xbd800000,0xbd35bd35,0xbd80,0x3d35bd35,
0xbd80,0x3d6d3cc4,0xbd353d35,0xbcc4bd6d,0xbd553d0e,0xbc48bd7b,0x3d7b3c48,0xbd0e3d55,0xbd800000,0x3cc4bd6d,0x3d353d35,0xbd6d3cc4,0x3d0e3d55,0xbd7b3c48,0x3c48bd7b,0x3d553d0e,
0x3d80,0xbd6dbcc4,0x3d35bd35,0x3cc43d6d,0x3d55bd0e,0x3c483d7b,0xbd7bbc48,0x3d0ebd55,0x3d800000,0xbcc43d6d,0xbd35bd35,0x3d6dbcc4,0xbd0ebd55,0x3d7bbc48,0xbc483d7b,0xbd55bd0e,
0xbc483d7b,0xbd0e3d55,0xbd553d0e,0xbd7b3c48,0xbd80,0x3cc4bd6d,0x3d35bd35,0x3d6dbcc4,0x3d7b3c48,0x3d553d0e,0x3d0e3d55,0x3c483d7b,0xbd800000,0xbd6dbcc4,0xbd35bd35,0xbcc4bd6d,
0x3c48bd7b,0x3d0ebd55,0x3d55bd0e,0x3d7bbc48,0x3d80,0xbcc43d6d,0xbd353d35,0xbd6d3cc4,0xbd7bbc48,0xbd55bd0e,0xbd0ebd55,0xbc48bd7b,0x3d800000,0x3d6d3cc4,0x3d353d35,0x3cc43d6d,
0x80003d80,0x80003d80,0x80003d80,0x80003d80,0x8000bd80,0x8000bd80,0x8000bd80,0x8000bd80,0x80003d80,0x80003d80,0x80003d80,0x80003d80,0x8000bd80,0x8000bd80,0x8000bd80,0x8000bd80,
0x80003d80,0x80003d80,0x80003d80,0x80003d80,0x8000bd80,0x8000bd80,0x8000bd80,0x8000bd80,0x80003d80,0x80003d80,0x80003d80,0x80003d80,0x8000bd80,0x8000bd80,0x8000bd80,0x8000bd80,
0xbd35bd35,0xbd353d35,0x3d353d35,0x3d35bd35,0x80003d80,0x3d800000,0x8000bd80,0xbd800000,0xbd35bd35,0xbd353d35,0x3d353d35,0x3d35bd35,0x80003d80,0x3d800000,0x8000bd80,0xbd800000,
0xbd35bd35,0xbd353d35,0x3d353d35,0x3d35bd35,0x80003d80,0x3d800000,0x8000bd80,0xbd800000,0xbd35bd35,0xbd353d35,0x3d353d35,0x3d35bd35,0x80003d80,0x3d800000,0x8000bd80,0xbd800000,
0x3d800000,0x3d6dbcc4,0x3d35bd35,0x3cc4bd6d,0xbd7b3c48,0xbd553d0e,0xbd0e3d55,0xbc483d7b,0x80003d80,0x3cc43d6d,0x3d353d35,0x3d6d3cc4,0xbc48bd7b,0xbd0ebd55,0xbd55bd0e,0xbd7bbc48,
0xbd800000,0xbd6d3cc4,0xbd353d35,0xbcc43d6d,0x3d7bbc48,0x3d55bd0e,0x3d0ebd55,0x3c48bd7b,0x8000bd80,0xbcc4bd6d,0xbd35bd35,0xbd6dbcc4,0x3c483d7b,0x3d0e3d55,0x3d553d0e,0x3d7b3c48,
0xbd0e3d55,0x3d7b3c48,0xbc48bd7b,0xbd553d0e,0x3d800000,0xbcc4bd6d,0xbd353d35,0x3d6d3cc4,0xbd55bd0e,0xbc483d7b,0x3d7bbc48,0xbd0ebd55,0x80003d80,0x3d6dbcc4,0xbd35bd35,0xbcc43d6d,
0x3d0ebd55,0xbd7bbc48,0x3c483d7b,0x3d55bd0e,0xbd800000,0x3cc43d6d,0x3d35bd35,0xbd6dbcc4,0x3d553d0e,0x3c48bd7b,0xbd7b3c48,0x3d0e3d55,0x8000bd80,0xbd6d3cc4,0x3d353d35,0x3cc4bd6d,
0x80003d80,0x3d353d35,0x3d800000,0x3d35bd35,0xbcc4bd6d,0xbd6dbcc4,0xbd6d3cc4,0xbcc43d6d,0x8000bd80,0xbd35bd35,0xbd800000,0xbd353d35,0x3cc43d6d,0x3d6d3cc4,0x3d6dbcc4,0x3cc4bd6d,
0x80003d80,0x3d353d35,0x3d800000,0x3d35bd35,0xbcc4bd6d,0xbd6dbcc4,0xbd6d3cc4,0xbcc43d6d,0x8000bd80,0xbd35bd35,0xbd800000,0xbd353d35,0x3cc43d6d,0x3d6d3cc4,0x3d6dbcc4,0x3cc4bd6d,
0xbd6dbcc4,0x3cc43d6d,0x3cc4bd6d,0xbd6d3cc4,0x80003d80,0x3d35bd35,0xbd800000,0x3d353d35,0x3d6d3cc4,0xbcc4bd6d,0xbcc43d6d,0x3d6dbcc4,0x8000bd80,0xbd353d35,0x3d800000,0xbd35bd35,
0xbd6dbcc4,0x3cc43d6d,0x3cc4bd6d,0xbd6d3cc4,0x80003d80,0x3d35bd35,0xbd800000,0x3d353d35,0x3d6d3cc4,0xbcc4bd6d,0xbcc43d6d,0x3d6dbcc4,0x8000bd80,0xbd353d35,0x3d800000,0xbd35bd35,
0x3d800000,0x3cc4bd6d,0xbd35bd35,0xbd6d3cc4,0xbd553d0e,0x3c483d7b,0x3d7b3c48,0x3d0ebd55,0x8000bd80,0xbd6dbcc4,0xbd353d35,0x3cc43d6d,0x3d0e3d55,0x3d7bbc48,0x3c48bd7b,0xbd55bd0e,
0xbd800000,0xbcc43d6d,0x3d353d35,0x3d6dbcc4,0x3d55bd0e,0xbc48bd7b,0xbd7bbc48,0xbd0e3d55,0x80003d80,0x3d6d3cc4,0x3d35bd35,0xbcc4bd6d,0xbd0ebd55,0xbd7b3c48,0xbc483d7b,0x3d553d0e,
0xbc483d7b,0x3d0ebd55,0xbd553d0e,0x3d7bbc48,0x3d800000,0xbd6dbcc4,0x3d353d35,0xbcc4bd6d,0x3d7b3c48,0xbd55bd0e,0x3d0e3d55,0xbc48bd7b,0x8000bd80,0xbcc43d6d,0x3d35bd35,0xbd6d3cc4,
0x3c48bd7b,0xbd0e3d55,0x3d55bd0e,0xbd7b3c48,0xbd800000,0x3d6d3cc4,0xbd35bd35,0x3cc43d6d,0xbd7bbc48,0x3d553d0e,0xbd0ebd55,0x3c483d7b,0x80003d80,0x3cc4bd6d,0xbd353d35,0x3d6dbcc4,
0x3d800000,0x3d800000,0x3d800000,0x3d800000,0xbd800000,0xbd800000,0xbd800000,0xbd800000,0x3d800000,0x3d800000,0x3d800000,0x3d800000,0xbd800000,0xbd800000,0xbd800000,0xbd800000,
0x3d800000,0x3d800000,0x3d800000,0x3d800000,0xbd800000,0xbd800000,0xbd800000,0xbd800000,0x3d800000,0x3d800000,0x3d800000,0x3d800000,0xbd800000,0xbd800000,0xbd800000,0xbd800000,
0xbd353d35,0x3d353d35,0x3d35bd35,0xbd35bd35,0x3d800000,0xbd80,0xbd800000,0x3d80,0xbd353d35,0x3d353d35,0x3d35bd35,0xbd35bd35,0x3d800000,0xbd80,0xbd800000,0x3d80,
0xbd353d35,0x3d353d35,0x3d35bd35,0xbd35bd35,0x3d800000,0xbd80,0xbd800000,0x3d80,0xbd353d35,0x3d353d35,0x3d35bd35,0xbd35bd35,0x3d800000,0xbd80,0xbd800000,0x3d80,
0xbd80,0xbcc4bd6d,0xbd35bd35,0xbd6dbcc4,0x3c483d7b,0x3d0e3d55,0x3d553d0e,0x3d7b3c48,0x3d800000,0x3d6dbcc4,0x3d35bd35,0x3cc4bd6d,0xbd7b3c48,0xbd553d0e,0xbd0e3d55,0xbc483d7b,
0x3d80,0x3cc43d6d,0x3d353d35,0x3d6d3cc4,0xbc48bd7b,0xbd0ebd55,0xbd55bd0e,0xbd7bbc48,0xbd800000,0xbd6d3cc4,0xbd353d35,0xbcc43d6d,0x3d7bbc48,0x3d55bd0e,0x3d0ebd55,0x3c48bd7b,
0x3d553d0e,0x3c48bd7b,0xbd7b3c48,0x3d0e3d55,0xbd80,0xbd6d3cc4,0x3d353d35,0x3cc4bd6d,0xbd0e3d55,0x3d7b3c48,0xbc48bd7b,0xbd553d0e,0x3d800000,0xbcc4bd6d,0xbd353d35,0x3d6d3cc4,
0xbd55bd0e,0xbc483d7b,0x3d7bbc48,0xbd0ebd55,0x3d80,0x3d6dbcc4,0xbd35bd35,0xbcc43d6d,0x3d0ebd55,0xbd7bbc48,0x3c483d7b,0x3d55bd0e,0xbd800000,0x3cc43d6d,0x3d35bd35,0xbd6dbcc4,
0x3d800000,0x3d35bd35,0xbd80,0xbd35bd35,0xbd6d3cc4,0xbcc43d6d,0x3cc43d6d,0x3d6d3cc4,0xbd800000,0xbd353d35,0x3d80,0x3d353d35,0x3d6dbcc4,0x3cc4bd6d,0xbcc4bd6d,0xbd6dbcc4,
0x3d800000,0x3d35bd35,0xbd80,0xbd35bd35,0xbd6d3cc4,0xbcc43d6d,0x3cc43d6d,0x3d6d3cc4,0xbd800000,0xbd353d35,0x3d80,0x3d353d35,0x3d6dbcc4,0x3cc4bd6d,0xbcc4bd6d,0xbd6dbcc4,
0xbcc43d6d,0x3d6dbcc4,0xbd6dbcc4,0x3cc43d6d,0x3d800000,0xbd35bd35,0x3d80,0x3d35bd35,0x3cc4bd6d,0xbd6d3cc4,0x3d6d3cc4,0xbcc4bd6d,0xbd800000,0x3d353d35,0xbd80,0xbd353d35,
0xbcc43d6d,0x3d6dbcc4,0xbd6dbcc4,0x3cc43d6d,0x3d800000,0xbd35bd35,0x3d80,0x3d35bd35,0x3cc4bd6d,0xbd6d3cc4,0x3d6d3cc4,0xbcc4bd6d,0xbd800000,0x3d353d35,0xbd80,0xbd353d35,
0xbd80,0xbd6dbcc4,0xbd353d35,0x3cc43d6d,0x3d0e3d55,0x3d7bbc48,0x3c48bd7b,0xbd55bd0e,0xbd800000,0xbcc43d6d,0x3d353d35,0x3d6dbcc4,0x3d55bd0e,0xbc48bd7b,0xbd7bbc48,0xbd0e3d55,
0x3d80,0x3d6d3cc4,0x3d35bd35,0xbcc4bd6d,0xbd0ebd55,0xbd7b3c48,0xbc483d7b,0x3d553d0e,0x3d800000,0x3cc4bd6d,0xbd35bd35,0xbd6d3cc4,0xbd553d0e,0x3c483d7b,0x3d7b3c48,0x3d0ebd55,
0x3d7b3c48,0xbd55bd0e,0x3d0e3d55,0xbc48bd7b,0xbd80,0xbcc43d6d,0x3d35bd35,0xbd6d3cc4,0x3c48bd7b,0xbd0e3d55,0x3d55bd0e,0xbd7b3c48,0xbd800000,0x3d6d3cc4,0xbd35bd35,0x3cc43d6d,
0xbd7bbc48,0x3d553d0e,0xbd0ebd55,0x3c483d7b,0x3d80,0x3cc4bd6d,0xbd353d35,0x3d6dbcc4,0xbc483d7b,0x3d0ebd55,0xbd553d0e,0x3d7bbc48,0x3d800000,0xbd6dbcc4,0x3d353d35,0xbcc4bd6d,
0x80003d80,0x8000bd80,0x80003d80,0x8000bd80,0xbd800000,0x3d800000,0xbd800000,0x3d800000,0x80003d80,0x8000bd80,0x80003d80,0x8000bd80,0xbd800000,0x3d800000,0xbd800000,0x3d800000,
0x80003d80,0x8000bd80,0x80003d80,0x8000bd80,0xbd800000,0x3d800000,0xbd800000,0x3d800000,0x80003d80,0x8000bd80,0x80003d80,0x8000bd80,0xbd800000,0x3d800000,0xbd800000,0x3d800000,
0xbd353d35,0xbd35bd35,0x3d35bd35,0x3d353d35,0x80003d80,0xbd800000,0x8000bd80,0x3d800000,0xbd353d35,0xbd35bd35,0x3d35bd35,0x3d353d35,0x80003d80,0xbd800000,0x8000bd80,0x3d800000,
0xbd353d35,0xbd35bd35,0x3d35bd35,0x3d353d35,0x80003d80,0xbd800000,0x8000bd80,0x3d800000,0xbd353d35,0xbd35bd35,0x3d35bd35,0x3d353d35,0x80003d80,0xbd800000,0x8000bd80,0x3d800000,
0x3d800000,0xbd6d3cc4,0x3d35bd35,0xbcc43d6d,0x3c483d7b,0xbd0ebd55,0x3d553d0e,0xbd7bbc48,0x80003d80,0xbcc4bd6d,0x3d353d35,0xbd6dbcc4,0xbd7b3c48,0x3d55bd0e,0xbd0e3d55,0x3c48bd7b,
0xbd800000,0x3d6dbcc4,0xbd353d35,0x3cc4bd6d,0xbc48bd7b,0x3d0e3d55,0xbd55bd0e,0x3d7b3c48,0x8000bd80,0x3cc43d6d,0xbd35bd35,0x3d6d3cc4,0x3d7bbc48,0xbd553d0e,0x3d0ebd55,0xbc483d7b,
0x3d553d0e,0xbc483d7b,0xbd7b3c48,0xbd0ebd55,0x3d800000,0x3cc43d6d,0xbd353d35,0xbd6dbcc4,0xbd0e3d55,0xbd7bbc48,0xbc48bd7b,0x3d55bd0e,0x80003d80,0xbd6d3cc4,0xbd35bd35,0x3cc4bd6d,
0xbd55bd0e,0x3c48bd7b,0x3d7bbc48,0x3d0e3d55,0xbd800000,0xbcc4bd6d,0x3d35bd35,0x3d6d3cc4,0x3d0ebd55,0x3d7b3c48,0x3c483d7b,0xbd553d0e,0x8000bd80,0x3d6dbcc4,0x3d353d35,0xbcc43d6d,
0x80003d80,0xbd35bd35,0x3d800000,0xbd353d35,0xbd6d3cc4,0x3cc4bd6d,0x3cc43d6d,0xbd6dbcc4,0x8000bd80,0x3d353d35,0xbd800000,0x3d35bd35,0x3d6dbcc4,0xbcc43d6d,0xbcc4bd6d,0x3d6d3cc4,
0x80003d80,0xbd35bd35,0x3d800000,0xbd353d35,0xbd6d3cc4,0x3cc4bd6d,0x3cc43d6d,0xbd6dbcc4,0x8000bd80,0x3d353d35,0xbd800000,0x3d35bd35,0x3d6dbcc4,0xbcc43d6d,0xbcc4bd6d,0x3d6d3cc4,
0xbcc43d6d,0xbd6d3cc4,0xbd6dbcc4,0xbcc4bd6d,0x80003d80,0xbd353d35,0xbd800000,0xbd35bd35,0x3cc4bd6d,0x3d6dbcc4,0x3d6d3cc4,0x3cc43d6d,0x8000bd80,0x3d35bd35,0x3d800000,0x3d353d35,
0xbcc43d6d,0xbd6d3cc4,0xbd6dbcc4,0xbcc4bd6d,0x80003d80,0xbd353d35,0xbd800000,0xbd35bd35,0x3cc4bd6d,0x3d6dbcc4,0x3d6d3cc4,0x3cc43d6d,0x8000bd80,0x3d35bd35,0x3d800000,0x3d353d35,
0x3d800000,0xbcc43d6d,0xbd35bd35,0x3d6dbcc4,0x3d0e3d55,0xbd7b3c48,0x3c48bd7b,0x3d553d0e,0x8000bd80,0x3d6d3cc4,0xbd353d35,0xbcc4bd6d,0x3d55bd0e,0x3c483d7b,0xbd7bbc48,0x3d0ebd55,
0xbd800000,0x3cc4bd6d,0x3d353d35,0xbd6d3cc4,0xbd0ebd55,0x3d7bbc48,0xbc483d7b,0xbd55bd0e,0x80003d80,0xbd6dbcc4,0x3d35bd35,0x3cc43d6d,0xbd553d0e,0xbc48bd7b,0x3d7b3c48,0xbd0e3d55,
0x3d7b3c48,0x3d553d0e,0x3d0e3d55,0x3c483d7b,0x3d800000,0x3d6d3cc4,0x3d353d35,0x3cc43d6d,0x3c48bd7b,0x3d0ebd55,0x3d55bd0e,0x3d7bbc48,0x8000bd80,0x3cc4bd6d,0x3d35bd35,0x3d6dbcc4,
0xbd7bbc48,0xbd55bd0e,0xbd0ebd55,0xbc48bd7b,0xbd800000,0xbd6dbcc4,0xbd35bd35,0xbcc4bd6d,0xbc483d7b,0xbd0e3d55,0xbd553d0e,0xbd7b3c48,0x80003d80,0xbcc43d6d,0xbd353d35,0xbd6d3cc4,
0x3d800000,0xbd800000,0x3d800000,0xbd800000,0x3d80,0xbd80,0x3d80,0xbd80,0x3d800000,0xbd800000,0x3d800000,0xbd800000,0x3d80,0xbd80,0x3d80,0xbd80,
0x3d800000,0xbd800000,0x3d800000,0xbd800000,0x3d80,0xbd80,0x3d80,0xbd80,0x3d800000,0xbd800000,0x3d800000,0xbd800000,0x3d80,0xbd80,0x3d80,0xbd80,
0x3d353d35,0xbd353d35,0xbd35bd35,0x3d35bd35,0x3d800000,0x3d80,0xbd800000,0xbd80,0x3d353d35,0xbd353d35,0xbd35bd35,0x3d35bd35,0x3d800000,0x3d80,0xbd800000,0xbd80,
0x3d353d35,0xbd353d35,0xbd35bd35,0x3d35bd35,0x3d800000,0x3d80,0xbd800000,0xbd80,0x3d353d35,0xbd353d35,0xbd35bd35,0x3d35bd35,0x3d800000,0x3d80,0xbd800000,0xbd80,
0xbd80,0x3cc43d6d,0xbd35bd35,0x3d6d3cc4,0x3d7bbc48,0xbd553d0e,0x3d0ebd55,0xbc483d7b,0x3d800000,0xbd6d3cc4,0x3d35bd35,0xbcc43d6d,0x3c483d7b,0xbd0ebd55,0x3d553d0e,0xbd7bbc48,
0x3d80,0xbcc4bd6d,0x3d353d35,0xbd6dbcc4,0xbd7b3c48,0x3d55bd0e,0xbd0e3d55,0x3c48bd7b,0xbd800000,0x3d6dbcc4,0xbd353d35,0x3cc4bd6d,0xbc48bd7b,0x3d0e3d55,0xbd55bd0e,0x3d7b3c48,
0x3d0ebd55,0x3d7b3c48,0x3c483d7b,0xbd553d0e,0xbd80,0x3d6dbcc4,0x3d353d35,0xbcc43d6d,0x3d553d0e,0xbc483d7b,0xbd7b3c48,0xbd0ebd55,0x3d800000,0x3cc43d6d,0xbd353d35,0xbd6dbcc4,
0xbd0e3d55,0xbd7bbc48,0xbc48bd7b,0x3d55bd0e,0x3d80,0xbd6d3cc4,0xbd35bd35,0x3cc4bd6d,0xbd55bd0e,0x3c48bd7b,0x3d7bbc48,0x3d0e3d55,0xbd800000,0xbcc4bd6d,0x3d35bd35,0x3d6d3cc4,
0x3d800000,0xbd353d35,0xbd80,0x3d353d35,0x3cc43d6d,0xbd6dbcc4,0x3d6dbcc4,0xbcc43d6d,0xbd800000,0x3d35bd35,0x3d80,0xbd35bd35,0xbcc4bd6d,0x3d6d3cc4,0xbd6d3cc4,0x3cc4bd6d,
0x3d800000,0xbd353d35,0xbd80,0x3d353d35,0x3cc43d6d,0xbd6dbcc4,0x3d6dbcc4,0xbcc43d6d,0xbd800000,0x3d35bd35,0x3d80,0xbd35bd35,0xbcc4bd6d,0x3d6d3cc4,0xbd6d3cc4,0x3cc4bd6d,
0x3d6d3cc4,0x3cc43d6d,0xbcc43d6d,0xbd6d3cc4,0x3d800000,0x3d353d35,0x3d80,0xbd353d35,0xbd6dbcc4,0xbcc4bd6d,0x3cc4bd6d,0x3d6dbcc4,0xbd800000,0xbd35bd35,0xbd80,0x3d35bd35,
0x3d6d3cc4,0x3cc43d6d,0xbcc43d6d,0xbd6d3cc4,0x3d800000,0x3d353d35,0x3d80,0xbd353d35,0xbd6dbcc4,0xbcc4bd6d,0x3cc4bd6d,0x3d6dbcc4,0xbd800000,0xbd35bd35,0xbd80,0x3d35bd35,
0xbd80,0x3d6d3cc4,0xbd353d35,0xbcc4bd6d,0x3d55bd0e,0x3c483d7b,0xbd7bbc48,0x3d0ebd55,0xbd800000,0x3cc4bd6d,0x3d353d35,0xbd6d3cc4,0xbd0ebd55,0x3d7bbc48,0xbc483d7b,0xbd55bd0e,
0x3d80,0xbd6dbcc4,0x3d35bd35,0x3cc43d6d,0xbd553d0e,0xbc48bd7b,0x3d7b3c48,0xbd0e3d55,0x3d800000,0xbcc43d6d,0xbd35bd35,0x3d6dbcc4,0x3d0e3d55,0xbd7b3c48,0x3c48bd7b,0x3d553d0e,
0x3c48bd7b,0x3d0ebd55,0x3d55bd0e,0x3d7bbc48,0xbd80,0x3cc4bd6d,0x3d35bd35,0x3d6dbcc4,0xbd7bbc48,0xbd55bd0e,0xbd0ebd55,0xbc48bd7b,0xbd800000,0xbd6dbcc4,0xbd35bd35,0xbcc4bd6d,
0xbc483d7b,0xbd0e3d55,0xbd553d0e,0xbd7b3c48,0x3d80,0xbcc43d6d,0xbd353d35,0xbd6d3cc4,0x3d7b3c48,0x3d553d0e,0x3d0e3d55,0x3c483d7b,0x3d800000,0x3d6d3cc4,0x3d353d35,0x3cc43d6d,
0x3d80,0x3d80,0x3d80,0x3d80,0x3d80,0x3d80,0x3d80,0x3d80,0x3d80,0x3d80,0x3d80,0x3d80,0x3d80,0x3d80,0x3d80,0x3d80,
0x3d80,0x3d80,0x3d80,0x3d80,0x3d80,0x3d80,0x3d80,0x3d80,0x3d80,0x3d80,0x3d80,0x3d80,0x3d80,0x3d80,0x3d80,0x3d80,
0xbd353d35,0xbd553d0e,0xbd6d3cc4,0xbd7b3c48,0x3d80,0xbc483d7b,0xbcc43d6d,0xbd0e3d55,0xbd35bd35,0xbd0ebd55,0xbcc4bd6d,0xbc48bd7b,0xbd800000,0xbd7bbc48,0xbd6dbcc4,0xbd55bd0e,
0x3d35bd35,0x3d55bd0e,0x3d6dbcc4,0x3d7bbc48,0xbd80,0x3c48bd7b,0x3cc4bd6d,0x3d0ebd55,0x3d353d35,0x3d0e3d55,0x3cc43d6d,0x3c483d7b,0x3d800000,0x3d7b3c48,0x3d6d3cc4,0x3d553d0e,
0xbd80,0x3cc4bd6d,0x3d35bd35,0x3d6dbcc4,0x3d800000,0x3d6d3cc4,0x3d353d35,0x3cc43d6d,0x3d80,0xbcc43d6d,0xbd353d35,0xbd6d3cc4,0xbd800000,0xbd6dbcc4,0xbd35bd35,0xbcc4bd6d,
0xbd80,0x3cc4bd6d,0x3d35bd35,0x3d6dbcc4,0x3d800000,0x3d6d3cc4,0x3d353d35,0x3cc43d6d,0x3d80,0xbcc43d6d,0xbd353d35,0xbd6d3cc4,0xbd800000,0xbd6dbcc4,0xbd35bd35,0xbcc4bd6d,
0xbd353d35,0xbd7b3c48,0xbd6dbcc4,0xbd0ebd55,0x3d800000,0x3d553d0e,0x3cc43d6d,0xbc483d7b,0xbd35bd35,0xbc48bd7b,0x3cc4bd6d,0x3d55bd0e,0x3d80,0xbd0e3d55,0xbd6d3cc4,0xbd7bbc48,
0x3d35bd35,0x3d7bbc48,0x3d6d3cc4,0x3d0e3d55,0xbd800000,0xbd55bd0e,0xbcc4bd6d,0x3c48bd7b,0x3d353d35,0x3c483d7b,0xbcc43d6d,0xbd553d0e,0xbd80,0x3d0ebd55,0x3d6dbcc4,0x3d7b3c48,
0x3d80,0xbd353d35,0xbd800000,0xbd35bd35,0xbd80,0x3d35bd35,0x3d800000,0x3d353d35,0x3d80,0xbd353d35,0xbd800000,0xbd35bd35,0xbd80,0x3d35bd35,0x3d800000,0x3d353d35,
0x3d80,0xbd353d35,0xbd800000,0xbd35bd35,0xbd80,0x3d35bd35,0x3d800000,0x3d353d35,0x3d80,0xbd353d35,0xbd800000,0xbd35bd35,0xbd80,0x3d35bd35,0x3d800000,0x3d353d35,
0xbd353d35,0xbd7bbc48,0xbcc4bd6d,0x3d0ebd55,0xbd80,0x3d55bd0e,0x3d6d3cc4,0x3c483d7b,0xbd35bd35,0x3c48bd7b,0x3d6dbcc4,0x3d553d0e,0x3d800000,0x3d0e3d55,0xbcc43d6d,0xbd7b3c48,
0x3d35bd35,0x3d7b3c48,0x3cc43d6d,0xbd0e3d55,0x3d80,0xbd553d0e,0xbd6dbcc4,0xbc48bd7b,0x3d353d35,0xbc483d7b,0xbd6d3cc4,0xbd55bd0e,0xbd800000,0xbd0ebd55,0x3cc4bd6d,0x3d7bbc48,
0xbd80,0x3d6dbcc4,0x3d353d35,0xbcc43d6d,0xbd800000,0xbcc4bd6d,0x3d35bd35,0x3d6d3cc4,0x3d80,0xbd6d3cc4,0xbd35bd35,0x3cc4bd6d,0x3d800000,0x3cc43d6d,0xbd353d35,0xbd6dbcc4,
0xbd80,0x3d6dbcc4,0x3d353d35,0xbcc43d6d,0xbd800000,0xbcc4bd6d,0x3d35bd35,0x3d6d3cc4,0x3d80,0xbd6d3cc4,0xbd35bd35,0x3cc4bd6d,0x3d800000,0x3cc43d6d,0xbd353d35,0xbd6dbcc4,
0xbd353d35,0xbd55bd0e,0x3cc4bd6d,0x3d7b3c48,0xbd800000,0xbc48bd7b,0x3d6dbcc4,0x3d0e3d55,0xbd35bd35,0x3d0ebd55,0x3d6d3cc4,0xbc483d7b,0xbd80,0x3d7bbc48,0x3cc43d6d,0xbd553d0e,
0x3d35bd35,0x3d553d0e,0xbcc43d6d,0xbd7bbc48,0x3d800000,0x3c483d7b,0xbd6d3cc4,0xbd0ebd55,0x3d353d35,0xbd0e3d55,0xbd6dbcc4,0x3c48bd7b,0x3d80,0xbd7b3c48,0xbcc4bd6d,0x3d55bd0e,
0xbd800000,0xbd800000,0xbd800000,0xbd800000,0xbd800000,0xbd800000,0xbd800000,0xbd800000,0xbd800000,0xbd800000,0xbd800000,0xbd800000,0xbd800000,0xbd800000,0xbd800000,0xbd800000,
0xbd800000,0xbd800000,0xbd800000,0xbd800000,0xbd800000,0xbd800000,0xbd800000,0xbd800000,0xbd800000,0xbd800000,0xbd800000,0xbd800000,0xbd800000,0xbd800000,0xbd800000,0xbd800000,
0xbd35bd35,0xbd0ebd55,0xbcc4bd6d,0xbc48bd7b,0xbd800000,0xbd7bbc48,0xbd6dbcc4,0xbd55bd0e,0x3d35bd35,0x3d55bd0e,0x3d6dbcc4,0x3d7bbc48,0x8000bd80,0x3c48bd7b,0x3cc4bd6d,0x3d0ebd55,
0x3d353d35,0x3d0e3d55,0x3cc43d6d,0x3c483d7b,0x3d800000,0x3d7b3c48,0x3d6d3cc4,0x3d553d0e,0xbd353d35,0xbd553d0e,0xbd6d3cc4,0xbd7b3c48,0x80003d80,0xbc483d7b,0xbcc43d6d,0xbd0e3d55,
0x3d800000,0x3d6d3cc4,0x3d353d35,0x3cc43d6d,0x80003d80,0xbcc43d6d,0xbd353d35,0xbd6d3cc4,0xbd800000,0xbd6dbcc4,0xbd35bd35,0xbcc4bd6d,0x8000bd80,0x3cc4bd6d,0x3d35bd35,0x3d6dbcc4,
0x3d800000,0x3d6d3cc4,0x3d353d35,0x3cc43d6d,0x80003d80,0xbcc43d6d,0xbd353d35,0xbd6d3cc4,0xbd800000,0xbd6dbcc4,0xbd35bd35,0xbcc4bd6d,0x8000bd80,0x3cc4bd6d,0x3d35bd35,0x3d6dbcc4,
0xbd35bd35,0xbc48bd7b,0x3cc4bd6d,0x3d55bd0e,0x80003d80,0xbd0e3d55,0xbd6d3cc4,0xbd7bbc48,0x3d35bd35,0x3d7bbc48,0x3d6d3cc4,0x3d0e3d55,0xbd800000,0xbd55bd0e,0xbcc4bd6d,0x3c48bd7b,
0x3d353d35,0x3c483d7b,0xbcc43d6d,0xbd553d0e,0x8000bd80,0x3d0ebd55,0x3d6dbcc4,0x3d7b3c48,0xbd353d35,0xbd7b3c48,0xbd6dbcc4,0xbd0ebd55,0x3d800000,0x3d553d0e,0x3cc43d6d,0xbc483d7b,
0xbd800000,0xbd35bd35,0x8000bd80,0x3d35bd35,0x3d800000,0x3d353d35,0x80003d80,0xbd353d35,0xbd800000,0xbd35bd35,0x8000bd80,0x3d35bd35,0x3d800000,0x3d353d35,0x80003d80,0xbd353d35,
0xbd800000,0xbd35bd35,0x8000bd80,0x3d35bd35,0x3d800000,0x3d353d35,0x80003d80,0xbd353d35,0xbd800000,0xbd35bd35,0x8000bd80,0x3d35bd35,0x3d800000,0x3d353d35,0x80003d80,0xbd353d35,
0xbd35bd35,0x3c48bd7b,0x3d6dbcc4,0x3d553d0e,0x3d800000,0x3d0e3d55,0xbcc43d6d,0xbd7b3c48,0x3d35bd35,0x3d7b3c48,0x3cc43d6d,0xbd0e3d55,0x80003d80,0xbd553d0e,0xbd6dbcc4,0xbc48bd7b,
0x3d353d35,0xbc483d7b,0xbd6d3cc4,0xbd55bd0e,0xbd800000,0xbd0ebd55,0x3cc4bd6d,0x3d7bbc48,0xbd353d35,0xbd7bbc48,0xbcc4bd6d,0x3d0ebd55,0x8000bd80,0x3d55bd0e,0x3d6d3cc4,0x3c483d7b,
0x3d800000,0x3cc43d6d,0xbd353d35,0xbd6dbcc4,0x8000bd80,0x3d6dbcc4,0x3d353d35,0xbcc43d6d,0xbd800000,0xbcc4bd6d,0x3d35bd35,0x3d6d3cc4,0x80003d80,0xbd6d3cc4,0xbd35bd35,0x3cc4bd6d,
0x3d800000,0x3cc43d6d,0xbd353d35,0xbd6dbcc4,0x8000bd80,0x3d6dbcc4,0x3d353d35,0xbcc43d6d,0xbd800000,0xbcc4bd6d,0x3d35bd35,0x3d6d3cc4,0x80003d80,0xbd6d3cc4,0xbd35bd35,0x3cc4bd6d,
0xbd35bd35,0x3d0ebd55,0x3d6d3cc4,0xbc483d7b,0x8000bd80,0x3d7bbc48,0x3cc43d6d,0xbd553d0e,0x3d35bd35,0x3d553d0e,0xbcc43d6d,0xbd7bbc48,0x3d800000,0x3c483d7b,0xbd6d3cc4,0xbd0ebd55,
0x3d353d35,0xbd0e3d55,0xbd6dbcc4,0x3c48bd7b,0x80003d80,0xbd7b3c48,0xbcc4bd6d,0x3d55bd0e,0xbd353d35,0xbd55bd0e,0x3cc4bd6d,0x3d7b3c48,0xbd800000,0xbc48bd7b,0x3d6dbcc4,0x3d0e3d55,
0x3d80,0xbd800000,0xbd80,0x3d800000,0x3d80,0xbd800000,0xbd80,0x3d800000,0x3d80,0xbd800000,0xbd80,0x3d800000,0x3d80,0xbd800000,0xbd80,0x3d800000,
0x3d80,0xbd800000,0xbd80,0x3d800000,0x3d80,0xbd800000,0xbd80,0x3d800000,0x3d80,0xbd800000,0xbd80,0x3d800000,0x3d80,0xbd800000,0xbd80,0x3d800000,
0xbd353d35,0xbd0ebd55,0x3d6dbcc4,0x3c483d7b,0x3d80,0xbd7bbc48,0x3cc4bd6d,0x3d553d0e,0xbd35bd35,0x3d55bd0e,0x3cc43d6d,0xbd7b3c48,0xbd800000,0x3c48bd7b,0x3d6d3cc4,0xbd0e3d55,
0x3d35bd35,0x3d0e3d55,0xbd6d3cc4,0xbc48bd7b,0xbd80,0x3d7b3c48,0xbcc43d6d,0xbd55bd0e,0x3d353d35,0xbd553d0e,0xbcc4bd6d,0x3d7bbc48,0x3d800000,0xbc483d7b,0xbd6dbcc4,0x3d0ebd55,
0xbd80,0x3d6d3cc4,0xbd353d35,0xbcc4bd6d,0x3d800000,0xbcc43d6d,0xbd35bd35,0x3d6dbcc4,0x3d80,0xbd6dbcc4,0x3d35bd35,0x3cc43d6d,0xbd800000,0x3cc4bd6d,0x3d353d35,0xbd6d3cc4,
0xbd80,0x3d6d3cc4,0xbd353d35,0xbcc4bd6d,0x3d800000,0xbcc43d6d,0xbd35bd35,0x3d6dbcc4,0x3d80,0xbd6dbcc4,0x3d35bd35,0x3cc43d6d,0xbd800000,0x3cc4bd6d,0x3d353d35,0xbd6d3cc4,
0xbd353d35,0xbc48bd7b,0x3d6d3cc4,0xbd553d0e,0x3d800000,0xbd0e3d55,0xbcc4bd6d,0x3d7b3c48,0xbd35bd35,0x3d7bbc48,0xbcc43d6d,0xbd0ebd55,0x3d80,0xbd55bd0e,0x3d6dbcc4,0xbc483d7b,
0x3d35bd35,0x3c483d7b,0xbd6dbcc4,0x3d55bd0e,0xbd800000,0x3d0ebd55,0x3cc43d6d,0xbd7bbc48,0x3d353d35,0xbd7b3c48,0x3cc4bd6d,0x3d0e3d55,0xbd80,0x3d553d0e,0xbd6d3cc4,0x3c48bd7b,
0x3d80,0xbd35bd35,0x3d800000,0xbd353d35,0xbd80,0x3d353d35,0xbd800000,0x3d35bd35,0x3d80,0xbd35bd35,0x3d800000,0xbd353d35,0xbd80,0x3d353d35,0xbd800000,0x3d35bd35,
0x3d80,0xbd35bd35,0x3d800000,0xbd353d35,0xbd80,0x3d353d35,0xbd800000,0x3d35bd35,0x3d80,0xbd35bd35,0x3d800000,0xbd353d35,0xbd80,0x3d353d35,0xbd800000,0x3d35bd35,
0xbd353d35,0x3c48bd7b,0x3cc43d6d,0xbd55bd0e,0xbd80,0x3d0e3d55,0xbd6dbcc4,0x3d7bbc48,0xbd35bd35,0x3d7b3c48,0xbd6d3cc4,0x3d0ebd55,0x3d800000,0xbd553d0e,0x3cc4bd6d,0x3c483d7b,
0x3d35bd35,0xbc483d7b,0xbcc4bd6d,0x3d553d0e,0x3d80,0xbd0ebd55,0x3d6d3cc4,0xbd7b3c48,0x3d353d35,0xbd7bbc48,0x3d6dbcc4,0xbd0e3d55,0xbd800000,0x3d55bd0e,0xbcc43d6d,0xbc48bd7b,
0xbd80,0x3cc43d6d,0xbd35bd35,0x3d6d3cc4,0xbd800000,0x3d6dbcc4,0xbd353d35,0x3cc4bd6d,0x3d80,0xbcc4bd6d,0x3d353d35,0xbd6dbcc4,0x3d800000,0xbd6d3cc4,0x3d35bd35,0xbcc43d6d,
0xbd80,0x3cc43d6d,0xbd35bd35,0x3d6d3cc4,0xbd800000,0x3d6dbcc4,0xbd353d35,0x3cc4bd6d,0x3d80,0xbcc4bd6d,0x3d353d35,0xbd6dbcc4,0x3d800000,0xbd6d3cc4,0x3d35bd35,0xbcc43d6d,
0xbd353d35,0x3d0ebd55,0xbcc43d6d,0x3c48bd7b,0xbd800000,0x3d7bbc48,0xbd6d3cc4,0x3d55bd0e,0xbd35bd35,0x3d553d0e,0xbd6dbcc4,0x3d7b3c48,0xbd80,0x3c483d7b,0xbcc4bd6d,0x3d0e3d55,
0x3d35bd35,0xbd0e3d55,0x3cc4bd6d,0xbc483d7b,0x3d800000,0xbd7b3c48,0x3d6dbcc4,0xbd553d0e,0x3d353d35,0xbd55bd0e,0x3d6d3cc4,0xbd7bbc48,0x3d80,0xbc48bd7b,0x3cc43d6d,0xbd0ebd55,
0xbd800000,0x8000bd80,0x3d800000,0x80003d80,0xbd800000,0x8000bd80,0x3d800000,0x80003d80,0xbd800000,0x8000bd80,0x3d800000,0x80003d80,0xbd800000,0x8000bd80,0x3d800000,0x80003d80,
0xbd800000,0x8000bd80,0x3d800000,0x80003d80,0xbd800000,0x8000bd80,0x3d800000,0x80003d80,0xbd800000,0x8000bd80,0x3d800000,0x80003d80,0xbd800000,0x8000bd80,0x3d800000,0x80003d80,
0xbd35bd35,0x3d55bd0e,0x3cc43d6d,0xbd7b3c48,0xbd800000,0x3c48bd7b,0x3d6d3cc4,0xbd0e3d55,0x3d35bd35,0x3d0e3d55,0xbd6d3cc4,0xbc48bd7b,0x8000bd80,0x3d7b3c48,0xbcc43d6d,0xbd55bd0e,
0x3d353d35,0xbd553d0e,0xbcc4bd6d,0x3d7bbc48,0x3d800000,0xbc483d7b,0xbd6dbcc4,0x3d0ebd55,0xbd353d35,0xbd0ebd55,0x3d6dbcc4,0x3c483d7b,0x80003d80,0xbd7bbc48,0x3cc4bd6d,0x3d553d0e,
0x3d800000,0xbcc43d6d,0xbd35bd35,0x3d6dbcc4,0x80003d80,0xbd6dbcc4,0x3d35bd35,0x3cc43d6d,0xbd800000,0x3cc4bd6d,0x3d353d35,0xbd6d3cc4,0x8000bd80,0x3d6d3cc4,0xbd353d35,0xbcc4bd6d,
0x3d800000,0xbcc43d6d,0xbd35bd35,0x3d6dbcc4,0x80003d80,0xbd6dbcc4,0x3d35bd35,0x3cc43d6d,0xbd800000,0x3cc4bd6d,0x3d353d35,0xbd6d3cc4,0x8000bd80,0x3d6d3cc4,0xbd353d35,0xbcc4bd6d,
0xbd35bd35,0x3d7bbc48,0xbcc43d6d,0xbd0ebd55,0x80003d80,0xbd55bd0e,0x3d6dbcc4,0xbc483d7b,0x3d35bd35,0x3c483d7b,0xbd6dbcc4,0x3d55bd0e,0xbd800000,0x3d0ebd55,0x3cc43d6d,0xbd7bbc48,
0x3d353d35,0xbd7b3c48,0x3cc4bd6d,0x3d0e3d55,0x8000bd80,0x3d553d0e,0xbd6d3cc4,0x3c48bd7b,0xbd353d35,0xbc48bd7b,0x3d6d3cc4,0xbd553d0e,0x3d800000,0xbd0e3d55,0xbcc4bd6d,0x3d7b3c48,
0xbd800000,0x3d35bd35,0x80003d80,0xbd35bd35,0x3d800000,0xbd353d35,0x8000bd80,0x3d353d35,0xbd800000,0x3d35bd35,0x80003d80,0xbd35bd35,0x3d800000,0xbd353d35,0x8000bd80,0x3d353d35,
0xbd800000,0x3d35bd35,0x80003d80,0xbd35bd35,0x3d800000,0xbd353d35,0x8000bd80,0x3d353d35,0xbd800000,0x3d35bd35,0x80003d80,0xbd35bd35,0x3d800000,0xbd353d35,0x8000bd80,0x3d353d35,
0xbd35bd35,0x3d7b3c48,0xbd6d3cc4,0x3d0ebd55,0x3d800000,0xbd553d0e,0x3cc4bd6d,0x3c483d7b,0x3d35bd35,0xbc483d7b,0xbcc4bd6d,0x3d553d0e,0x80003d80,0xbd0ebd55,0x3d6d3cc4,0xbd7b3c48,
0x3d353d35,0xbd7bbc48,0x3d6dbcc4,0xbd0e3d55,0xbd800000,0x3d55bd0e,0xbcc43d6d,0xbc48bd7b,0xbd353d35,0x3c48bd7b,0x3cc43d6d,0xbd55bd0e,0x8000bd80,0x3d0e3d55,0xbd6dbcc4,0x3d7bbc48,
0x3d800000,0xbd6d3cc4,0x3d35bd35,0xbcc43d6d,0x8000bd80,0x3cc43d6d,0xbd35bd35,0x3d6d3cc4,0xbd800000,0x3d6dbcc4,0xbd353d35,0x3cc4bd6d,0x80003d80,0xbcc4bd6d,0x3d353d35,0xbd6dbcc4,
0x3d800000,0xbd6d3cc4,0x3d35bd35,0xbcc43d6d,0x8000bd80,0x3cc43d6d,0xbd35bd35,0x3d6d3cc4,0xbd800000,0x3d6dbcc4,0xbd353d35,0x3cc4bd6d,0x80003d80,0xbcc4bd6d,0x3d353d35,0xbd6dbcc4,
0xbd35bd35,0x3d553d0e,0xbd6dbcc4,0x3d7b3c48,0x8000bd80,0x3c483d7b,0xbcc4bd6d,0x3d0e3d55,0x3d35bd35,0xbd0e3d55,0x3cc4bd6d,0xbc483d7b,0x3d800000,0xbd7b3c48,0x3d6dbcc4,0xbd553d0e,
0x3d353d35,0xbd55bd0e,0x3d6d3cc4,0xbd7bbc48,0x80003d80,0xbc48bd7b,0x3cc43d6d,0xbd0ebd55,0xbd353d35,0x3d0ebd55,0xbcc43d6d,0x3c48bd7b,0xbd800000,0x3d7bbc48,0xbd6d3cc4,0x3d55bd0e,
0x3d80,0xbd80,0x3d80,0xbd80,0x3d80,0xbd80,0x3d80,0xbd80,0x3d80,0xbd80,0x3d80,0xbd80,0x3d80,0xbd80,0x3d80,0xbd80,
0x3d80,0xbd80,0x3d80,0xbd80,0x3d80,0xbd80,0x3d80,0xbd80,0x3d80,0xbd80,0x3d80,0xbd80,0x3d80,0xbd80,0x3d80,0xbd80,
0xbd353d35,0x3d55bd0e,0xbd6d3cc4,0x3d7bbc48,0x3d80,0x3c48bd7b,0xbcc43d6d,0x3d0ebd55,0xbd35bd35,0x3d0e3d55,0xbcc4bd6d,0x3c483d7b,0xbd800000,0x3d7b3c48,0xbd6dbcc4,0x3d553d0e,
0x3d35bd35,0xbd553d0e,0x3d6dbcc4,0xbd7b3c48,0xbd80,0xbc483d7b,0x3cc4bd6d,0xbd0e3d55,0x3d353d35,0xbd0ebd55,0x3cc43d6d,0xbc48bd7b,0x3d800000,0xbd7bbc48,0x3d6d3cc4,0xbd55bd0e,
0xbd80,0xbcc43d6d,0x3d35bd35,0xbd6d3cc4,0x3d800000,0xbd6dbcc4,0x3d353d35,0xbcc4bd6d,0x3d80,0x3cc4bd6d,0xbd353d35,0x3d6dbcc4,0xbd800000,0x3d6d3cc4,0xbd35bd35,0x3cc43d6d,
0xbd80,0xbcc43d6d,0x3d35bd35,0xbd6d3cc4,0x3d800000,0xbd6dbcc4,0x3d353d35,0xbcc4bd6d,0x3d80,0x3cc4bd6d,0xbd353d35,0x3d6dbcc4,0xbd800000,0x3d6d3cc4,0xbd35bd35,0x3cc43d6d,
0xbd353d35,0x3d7bbc48,0xbd6dbcc4,0x3d0e3d55,0x3d800000,0xbd55bd0e,0x3cc43d6d,0x3c48bd7b,0xbd35bd35,0x3c483d7b,0x3cc4bd6d,0xbd553d0e,0x3d80,0x3d0ebd55,0xbd6d3cc4,0x3d7b3c48,
0x3d35bd35,0xbd7b3c48,0x3d6d3cc4,0xbd0ebd55,0xbd800000,0x3d553d0e,0xbcc4bd6d,0xbc483d7b,0x3d353d35,0xbc48bd7b,0xbcc43d6d,0x3d55bd0e,0xbd80,0xbd0e3d55,0x3d6dbcc4,0xbd7bbc48,
0x3d80,0x3d35bd35,0xbd800000,0x3d353d35,0xbd80,0xbd353d35,0x3d800000,0xbd35bd35,0x3d80,0x3d35bd35,0xbd800000,0x3d353d35,0xbd80,0xbd353d35,0x3d800000,0xbd35bd35,
0x3d80,0x3d35bd35,0xbd800000,0x3d353d35,0xbd80,0xbd353d35,0x3d800000,0xbd35bd35,0x3d80,0x3d35bd35,0xbd800000,0x3d353d35,0xbd80,0xbd353d35,0x3d800000,0xbd35bd35,
0xbd353d35,0x3d7b3c48,0xbcc4bd6d,0xbd0e3d55,0xbd80,0xbd553d0e,0x3d6d3cc4,0xbc48bd7b,0xbd35bd35,0xbc483d7b,0x3d6dbcc4,0xbd55bd0e,0x3d800000,0xbd0ebd55,0xbcc43d6d,0x3d7bbc48,
0x3d35bd35,0xbd7bbc48,0x3cc43d6d,0x3d0ebd55,0x3d80,0x3d55bd0e,0xbd6dbcc4,0x3c483d7b,0x3d353d35,0x3c48bd7b,0xbd6d3cc4,0x3d553d0e,0xbd800000,0x3d0e3d55,0x3cc4bd6d,0xbd7b3c48,
0xbd80,0xbd6d3cc4,0x3d353d35,0x3cc4bd6d,0xbd800000,0x3cc43d6d,0x3d35bd35,0xbd6dbcc4,0x3d80,0x3d6dbcc4,0xbd35bd35,0xbcc43d6d,0x3d800000,0xbcc4bd6d,0xbd353d35,0x3d6d3cc4,
0xbd80,0xbd6d3cc4,0x3d353d35,0x3cc4bd6d,0xbd800000,0x3cc43d6d,0x3d35bd35,0xbd6dbcc4,0x3d80,0x3d6dbcc4,0xbd35bd35,0xbcc43d6d,0x3d800000,0xbcc4bd6d,0xbd353d35,0x3d6d3cc4,
0xbd353d35,0x3d553d0e,0x3cc4bd6d,0xbd7bbc48,0xbd800000,0x3c483d7b,0x3d6dbcc4,0xbd0ebd55,0xbd35bd35,0xbd0e3d55,0x3d6d3cc4,0x3c48bd7b,0xbd80,0xbd7b3c48,0x3cc43d6d,0x3d55bd0e,
0x3d35bd35,0xbd55bd0e,0xbcc43d6d,0x3d7b3c48,0x3d800000,0xbc48bd7b,0xbd6d3cc4,0x3d0e3d55,0x3d353d35,0x3d0ebd55,0xbd6dbcc4,0xbc483d7b,0x3d80,0x3d7bbc48,0xbcc4bd6d,0xbd553d0e,
0xbd800000,0x3d800000,0xbd800000,0x3d800000,0xbd800000,0x3d800000,0xbd800000,0x3d800000,0xbd800000,0x3d800000,0xbd800000,0x3d800000,0xbd800000,0x3d800000,0xbd800000,0x3d800000,
0xbd800000,0x3d800000,0xbd800000,0x3d800000,0xbd800000,0x3d800000,0xbd800000,0x3d800000,0xbd800000,0x3d800000,0xbd800000,0x3d800000,0xbd800000,0x3d800000,0xbd800000,0x3d800000,
0xbd35bd35,0x3d0e3d55,0xbcc4bd6d,0x3c483d7b,0xbd800000,0x3d7b3c48,0xbd6dbcc4,0x3d553d0e,0x3d35bd35,0xbd553d0e,0x3d6dbcc4,0xbd7b3c48,0x8000bd80,0xbc483d7b,0x3cc4bd6d,0xbd0e3d55,
0x3d353d35,0xbd0ebd55,0x3cc43d6d,0xbc48bd7b,0x3d800000,0xbd7bbc48,0x3d6d3cc4,0xbd55bd0e,0xbd353d35,0x3d55bd0e,0xbd6d3cc4,0x3d7bbc48,0x80003d80,0x3c48bd7b,0xbcc43d6d,0x3d0ebd55,
0x3d800000,0xbd6dbcc4,0x3d353d35,0xbcc4bd6d,0x80003d80,0x3cc4bd6d,0xbd353d35,0x3d6dbcc4,0xbd800000,0x3d6d3cc4,0xbd35bd35,0x3cc43d6d,0x8000bd80,0xbcc43d6d,0x3d35bd35,0xbd6d3cc4,
0x3d800000,0xbd6dbcc4,0x3d353d35,0xbcc4bd6d,0x80003d80,0x3cc4bd6d,0xbd353d35,0x3d6dbcc4,0xbd800000,0x3d6d3cc4,0xbd35bd35,0x3cc43d6d,0x8000bd80,0xbcc43d6d,0x3d35bd35,0xbd6d3cc4,
0xbd35bd35,0x3c483d7b,0x3cc4bd6d,0xbd553d0e,0x80003d80,0x3d0ebd55,0xbd6d3cc4,0x3d7b3c48,0x3d35bd35,0xbd7b3c48,0x3d6d3cc4,0xbd0ebd55,0xbd800000,0x3d553d0e,0xbcc4bd6d,0xbc483d7b,
0x3d353d35,0xbc48bd7b,0xbcc43d6d,0x3d55bd0e,0x8000bd80,0xbd0e3d55,0x3d6dbcc4,0xbd7bbc48,0xbd353d35,0x3d7bbc48,0xbd6dbcc4,0x3d0e3d55,0x3d800000,0xbd55bd0e,0x3cc43d6d,0x3c48bd7b,
0xbd800000,0x3d353d35,0x8000bd80,0xbd353d35,0x3d800000,0xbd35bd35,0x80003d80,0x3d35bd35,0xbd800000,0x3d353d35,0x8000bd80,0xbd353d35,0x3d800000,0xbd35bd35,0x80003d80,0x3d35bd35,
0xbd800000,0x3d353d35,0x8000bd80,0xbd353d35,0x3d800000,0xbd35bd35,0x80003d80,0x3d35bd35,0xbd800000,0x3d353d35,0x8000bd80,0xbd353d35,0x3d800000,0xbd35bd35,0x80003d80,0x3d35bd35,
0xbd35bd35,0xbc483d7b,0x3d6dbcc4,0xbd55bd0e,0x3d800000,0xbd0ebd55,0xbcc43d6d,0x3d7bbc48,0x3d35bd35,0xbd7bbc48,0x3cc43d6d,0x3d0ebd55,0x80003d80,0x3d55bd0e,0xbd6dbcc4,0x3c483d7b,
0x3d353d35,0x3c48bd7b,0xbd6d3cc4,0x3d553d0e,0xbd800000,0x3d0e3d55,0x3cc4bd6d,0xbd7b3c48,0xbd353d35,0x3d7b3c48,0xbcc4bd6d,0xbd0e3d55,0x8000bd80,0xbd553d0e,0x3d6d3cc4,0xbc48bd7b,
0x3d800000,0xbcc4bd6d,0xbd353d35,0x3d6d3cc4,0x8000bd80,0xbd6d3cc4,0x3d353d35,0x3cc4bd6d,0xbd800000,0x3cc43d6d,0x3d35bd35,0xbd6dbcc4,0x80003d80,0x3d6dbcc4,0xbd35bd35,0xbcc43d6d,
0x3d800000,0xbcc4bd6d,0xbd353d35,0x3d6d3cc4,0x8000bd80,0xbd6d3cc4,0x3d353d35,0x3cc4bd6d,0xbd800000,0x3cc43d6d,0x3d35bd35,0xbd6dbcc4,0x80003d80,0x3d6dbcc4,0xbd35bd35,0xbcc43d6d,
0xbd35bd35,0xbd0e3d55,0x3d6d3cc4,0x3c48bd7b,0x8000bd80,0xbd7b3c48,0x3cc43d6d,0x3d55bd0e,0x3d35bd35,0xbd55bd0e,0xbcc43d6d,0x3d7b3c48,0x3d800000,0xbc48bd7b,0xbd6d3cc4,0x3d0e3d55,
0x3d353d35,0x3d0ebd55,0xbd6dbcc4,0xbc483d7b,0x80003d80,0x3d7bbc48,0xbcc4bd6d,0xbd553d0e,0xbd353d35,0x3d553d0e,0x3cc4bd6d,0xbd7bbc48,0xbd800000,0x3c483d7b,0x3d6dbcc4,0xbd0ebd55,
0x3d80,0x3d800000,0xbd80,0xbd800000,0x3d80,0x3d800000,0xbd80,0xbd800000,0x3d80,0x3d800000,0xbd80,0xbd800000,0x3d80,0x3d800000,0xbd80,0xbd800000,
0x3d80,0x3d800000,0xbd80,0xbd800000,0x3d80,0x3d800000,0xbd80,0xbd800000,0x3d80,0x3d800000,0xbd80,0xbd800000,0x3d80,0x3d800000,0xbd80,0xbd800000,
0xbd353d35,0x3d0e3d55,0x3d6dbcc4,0xbc48bd7b,0x3d80,0x3d7b3c48,0x3cc4bd6d,0xbd55bd0e,0xbd35bd35,0xbd553d0e,0x3cc43d6d,0x3d7bbc48,0xbd800000,0xbc483d7b,0x3d6d3cc4,0x3d0ebd55,
0x3d35bd35,0xbd0ebd55,0xbd6d3cc4,0x3c483d7b,0xbd80,0xbd7bbc48,0xbcc43d6d,0x3d553d0e,0x3d353d35,0x3d55bd0e,0xbcc4bd6d,0xbd7b3c48,0x3d800000,0x3c48bd7b,0xbd6dbcc4,0xbd0e3d55,
0xbd80,0xbd6dbcc4,0xbd353d35,0x3cc43d6d,0x3d800000,0x3cc4bd6d,0xbd35bd35,0xbd6d3cc4,0x3d80,0x3d6d3cc4,0x3d35bd35,0xbcc4bd6d,0xbd800000,0xbcc43d6d,0x3d353d35,0x3d6dbcc4,
0xbd80,0xbd6dbcc4,0xbd353d35,0x3cc43d6d,0x3d800000,0x3cc4bd6d,0xbd35bd35,0xbd6d3cc4,0x3d80,0x3d6d3cc4,0x3d35bd35,0xbcc4bd6d,0xbd800000,0xbcc43d6d,0x3d353d35,0x3d6dbcc4,
0xbd353d35,0x3c483d7b,0x3d6d3cc4,0x3d55bd0e,0x3d800000,0x3d0ebd55,0xbcc4bd6d,0xbd7bbc48,0xbd35bd35,0xbd7b3c48,0xbcc43d6d,0x3d0e3d55,0x3d80,0x3d553d0e,0x3d6dbcc4,0x3c48bd7b,
0x3d35bd35,0xbc48bd7b,0xbd6dbcc4,0xbd553d0e,0xbd800000,0xbd0e3d55,0x3cc43d6d,0x3d7b3c48,0x3d353d35,0x3d7bbc48,0x3cc4bd6d,0xbd0ebd55,0xbd80,0xbd55bd0e,0xbd6d3cc4,0xbc483d7b,
0x3d80,0x3d353d35,0x3d800000,0x3d35bd35,0xbd80,0xbd35bd35,0xbd800000,0xbd353d35,0x3d80,0x3d353d35,0x3d800000,0x3d35bd35,0xbd80,0xbd35bd35,0xbd800000,0xbd353d35,
0x3d80,0x3d353d35,0x3d800000,0x3d35bd35,0xbd80,0xbd35bd35,0xbd800000,0xbd353d35,0x3d80,0x3d353d35,0x3d800000,0x3d35bd35,0xbd80,0xbd35bd35,0xbd800000,0xbd353d35,
0xbd353d35,0xbc483d7b,0x3cc43d6d,0x3d553d0e,0xbd80,0xbd0ebd55,0xbd6dbcc4,0xbd7b3c48,0xbd35bd35,0xbd7bbc48,0xbd6d3cc4,0xbd0e3d55,0x3d800000,0x3d55bd0e,0x3cc4bd6d,0xbc48bd7b,
0x3d35bd35,0x3c48bd7b,0xbcc4bd6d,0xbd55bd0e,0x3d80,0x3d0e3d55,0x3d6d3cc4,0x3d7bbc48,0x3d353d35,0x3d7b3c48,0x3d6dbcc4,0x3d0ebd55,0xbd800000,0xbd553d0e,0xbcc43d6d,0x3c483d7b,
0xbd80,0xbcc4bd6d,0xbd35bd35,0xbd6dbcc4,0xbd800000,0xbd6d3cc4,0xbd353d35,0xbcc43d6d,0x3d80,0x3cc43d6d,0x3d353d35,0x3d6d3cc4,0x3d800000,0x3d6dbcc4,0x3d35bd35,0x3cc4bd6d,
0xbd80,0xbcc4bd6d,0xbd35bd35,0xbd6dbcc4,0xbd800000,0xbd6d3cc4,0xbd353d35,0xbcc43d6d,0x3d80,0x3cc43d6d,0x3d353d35,0x3d6d3cc4,0x3d800000,0x3d6dbcc4,0x3d35bd35,0x3cc4bd6d,
0xbd353d35,0xbd0e3d55,0xbcc43d6d,0xbc483d7b,0xbd800000,0xbd7b3c48,0xbd6d3cc4,0xbd553d0e,0xbd35bd35,0xbd55bd0e,0xbd6dbcc4,0xbd7bbc48,0xbd80,0xbc48bd7b,0xbcc4bd6d,0xbd0ebd55,
0x3d35bd35,0x3d0ebd55,0x3cc4bd6d,0x3c48bd7b,0x3d800000,0x3d7bbc48,0x3d6dbcc4,0x3d55bd0e,0x3d353d35,0x3d553d0e,0x3d6d3cc4,0x3d7b3c48,0x3d80,0x3c483d7b,0x3cc43d6d,0x3d0e3d55,
0xbd800000,0x80003d80,0x3d800000,0x8000bd80,0xbd800000,0x80003d80,0x3d800000,0x8000bd80,0xbd800000,0x80003d80,0x3d800000,0x8000bd80,0xbd800000,0x80003d80,0x3d800000,0x8000bd80,
0xbd800000,0x80003d80,0x3d800000,0x8000bd80,0xbd800000,0x80003d80,0x3d800000,0x8000bd80,0xbd800000,0x80003d80,0x3d800000,0x8000bd80,0xbd800000,0x80003d80,0x3d800000,0x8000bd80,
0xbd35bd35,0xbd553d0e,0x3cc43d6d,0x3d7bbc48,0xbd800000,0xbc483d7b,0x3d6d3cc4,0x3d0ebd55,0x3d35bd35,0xbd0ebd55,0xbd6d3cc4,0x3c483d7b,0x8000bd80,0xbd7bbc48,0xbcc43d6d,0x3d553d0e,
0x3d353d35,0x3d55bd0e,0xbcc4bd6d,0xbd7b3c48,0x3d800000,0x3c48bd7b,0xbd6dbcc4,0xbd0e3d55,0xbd353d35,0x3d0e3d55,0x3d6dbcc4,0xbc48bd7b,0x80003d80,0x3d7b3c48,0x3cc4bd6d,0xbd55bd0e,
0x3d800000,0x3cc4bd6d,0xbd35bd35,0xbd6d3cc4,0x80003d80,0x3d6d3cc4,0x3d35bd35,0xbcc4bd6d,0xbd800000,0xbcc43d6d,0x3d353d35,0x3d6dbcc4,0x8000bd80,0xbd6dbcc4,0xbd353d35,0x3cc43d6d,
0x3d800000,0x3cc4bd6d,0xbd35bd35,0xbd6d3cc4,0x80003d80,0x3d6d3cc4,0x3d35bd35,0xbcc4bd6d,0xbd800000,0xbcc43d6d,0x3d353d35,0x3d6dbcc4,0x8000bd80,0xbd6dbcc4,0xbd353d35,0x3cc43d6d,
0xbd35bd35,0xbd7b3c48,0xbcc43d6d,0x3d0e3d55,0x80003d80,0x3d553d0e,0x3d6dbcc4,0x3c48bd7b,0x3d35bd35,0xbc48bd7b,0xbd6dbcc4,0xbd553d0e,0xbd800000,0xbd0e3d55,0x3cc43d6d,0x3d7b3c48,
0x3d353d35,0x3d7bbc48,0x3cc4bd6d,0xbd0ebd55,0x8000bd80,0xbd55bd0e,0xbd6d3cc4,0xbc483d7b,0xbd353d35,0x3c483d7b,0x3d6d3cc4,0x3d55bd0e,0x3d800000,0x3d0ebd55,0xbcc4bd6d,0xbd7bbc48,
0xbd800000,0xbd353d35,0x80003d80,0x3d353d35,0x3d800000,0x3d35bd35,0x8000bd80,0xbd35bd35,0xbd800000,0xbd353d35,0x80003d80,0x3d353d35,0x3d800000,0x3d35bd35,0x8000bd80,0xbd35bd35,
0xbd800000,0xbd353d35,0x80003d80,0x3d353d35,0x3d800000,0x3d35bd35,0x8000bd80,0xbd35bd35,0xbd800000,0xbd353d35,0x80003d80,0x3d353d35,0x3d800000,0x3d35bd35,0x8000bd80,0xbd35bd35,
0xbd35bd35,0xbd7bbc48,0xbd6d3cc4,0xbd0e3d55,0x3d800000,0x3d55bd0e,0x3cc4bd6d,0xbc48bd7b,0x3d35bd35,0x3c48bd7b,0xbcc4bd6d,0xbd55bd0e,0x80003d80,0x3d0e3d55,0x3d6d3cc4,0x3d7bbc48,
0x3d353d35,0x3d7b3c48,0x3d6dbcc4,0x3d0ebd55,0xbd800000,0xbd553d0e,0xbcc43d6d,0x3c483d7b,0xbd353d35,0xbc483d7b,0x3cc43d6d,0x3d553d0e,0x8000bd80,0xbd0ebd55,0xbd6dbcc4,0xbd7b3c48,
0x3d800000,0x3d6dbcc4,0x3d35bd35,0x3cc4bd6d,0x8000bd80,0xbcc4bd6d,0xbd35bd35,0xbd6dbcc4,0xbd800000,0xbd6d3cc4,0xbd353d35,0xbcc43d6d,0x80003d80,0x3cc43d6d,0x3d353d35,0x3d6d3cc4,
0x3d800000,0x3d6dbcc4,0x3d35bd35,0x3cc4bd6d,0x8000bd80,0xbcc4bd6d,0xbd35bd35,0xbd6dbcc4,0xbd800000,0xbd6d3cc4,0xbd353d35,0xbcc43d6d,0x80003d80,0x3cc43d6d,0x3d353d35,0x3d6d3cc4,
0xbd35bd35,0xbd55bd0e,0xbd6dbcc4,0xbd7bbc48,0x8000bd80,0xbc48bd7b,0xbcc4bd6d,0xbd0ebd55,0x3d35bd35,0x3d0ebd55,0x3cc4bd6d,0x3c48bd7b,0x3d800000,0x3d7bbc48,0x3d6dbcc4,0x3d55bd0e,
0x3d353d35,0x3d553d0e,0x3d6d3cc4,0x3d7b3c48,0x80003d80,0x3c483d7b,0x3cc43d6d,0x3d0e3d55,0xbd353d35,0xbd0e3d55,0xbcc43d6d,0xbc483d7b,0xbd800000,0xbd7b3c48,0xbd6d3cc4,0xbd553d0e,
0x3d80,0xbb493d80,0xbbc93d7f,0xbc163d7d,0xbc483d7b,0xbc793d78,0xbc953d75,0xbcac3d71,0xbcc43d6d,0xbcdb3d67,0xbcf13d62,0xbd043d5c,0xbd0e3d55,0xbd183d4e,0xbd223d46,0xbd2c3d3e,
0xbd353d35,0xbd3e3d2c,0xbd463d22,0xbd4e3d18,0xbd553d0e,0xbd5c3d04,0xbd623cf1,0xbd673cdb,0xbd6d3cc4,0xbd713cac,0xbd753c95,0xbd783c79,0xbd7b3c48,0xbd7d3c16,0xbd7f3bc9,0xbd803b49,
0xbd553d0e,0xbd713cac,0xbd7f3bc9,0xbd7dbc16,0x3d80,0xbc793d78,0xbcf13d62,0xbd2c3d3e,0xbc48bd7b,0x3b49bd80,0x3c95bd75,0x3d04bd5c,0xbd6dbcc4,0xbd4ebd18,0xbd22bd46,0xbcdbbd67,
0x3d7b3c48,0x3d673cdb,0x3d463d22,0x3d183d4e,0x3d35bd35,0x3d5cbd04,0x3d75bc95,0x3d80bb49,0xbd0e3d55,0xbd3e3d2c,0xbd623cf1,0xbd783c79,0x3cc43d6d,0x3c163d7d,0xbbc93d7f,0xbcac3d71,
0x3cc4bd6d,0x3d3ebd2c,0x3d75bc95,0x3d7d3c16,0x3d553d0e,0x3d043d5c,0x3bc93d7f,0xbcac3d71,0x3d80,0xbcdb3d67,0xbd463d22,0xbd783c79,0xbd7bbc48,0xbd4ebd18,0xbcf1bd62,0xbb49bd80,
0x3d6dbcc4,0x3d803b49,0x3d623cf1,0x3d183d4e,0x3c483d7b,0xbc793d78,0xbd223d46,0xbd673cdb,0xbd353d35,0xbd713cac,0xbd7fbbc9,0xbd5cbd04,0xbd0ebd55,0xbc16bd7d,0x3c95bd75,0x3d2cbd3e,
0xbd7b3c48,0xbd67bcdb,0xbcf1bd62,0x3c16bd7d,0x3d6d3cc4,0x3d043d5c,0xbbc93d7f,0xbd2c3d3e,0xbd0ebd55,0x3b49bd80,0x3d22bd46,0x3d78bc79,0x3d80,0xbd183d4e,0xbd753c95,0xbd71bcac,
0x3d553d0e,0x3cac3d71,0xbc953d75,0xbd4e3d18,0xbcc4bd6d,0x3c79bd78,0x3d46bd22,0x3d80bb49,0xbc483d7b,0xbd3e3d2c,0xbd7f3bc9,0xbd5cbd04,0x3d35bd35,0x3d7dbc16,0x3d623cf1,0x3cdb3d67,
0xbd353d35,0xbd80bb49,0xbd22bd46,0x3c16bd7d,0x3d55bd0e,0x3d783c79,0x3cf13d62,0xbcac3d71,0xbd6d3cc4,0xbd67bcdb,0xbc95bd75,0x3d04bd5c,0x3d7bbc48,0x3d4e3d18,0x3bc93d7f,0xbd2c3d3e,
0x3d80,0xbd3e3d2c,0xbd7fbbc9,0xbd18bd4e,0x3c48bd7b,0x3d5cbd04,0x3d753c95,0x3cdb3d67,0xbcc43d6d,0xbd713cac,0xbd62bcf1,0xbc79bd78,0x3d0ebd55,0x3d7dbc16,0x3d463d22,0x3b493d80,
0xbd7bbc48,0xbcacbd71,0x3d22bd46,0x3d7d3c16,0x3d35bd35,0x3d783c79,0x3c953d75,0xbd2c3d3e,0x3d0ebd55,0x3d803b49,0x3cf13d62,0xbd043d5c,0x3cc43d6d,0xbd183d4e,0xbd7fbbc9,0xbcdbbd67,
0x3d55bd0e,0x3d673cdb,0x3bc93d7f,0xbd4e3d18,0x3d80,0xbd5c3d04,0xbd62bcf1,0xbb49bd80,0x3c483d7b,0xbd3e3d2c,0xbd75bc95,0xbc79bd78,0xbd6dbcc4,0xbc16bd7d,0x3d46bd22,0x3d713cac,
0x3d6dbcc4,0x3d2c3d3e,0xbcf13d62,0xbd7dbc16,0xbc48bd7b,0x3d5cbd04,0x3d463d22,0xbcac3d71,0xbd353d35,0xbd67bcdb,0x3bc9bd7f,0x3d78bc79,0x3d0e3d55,0xbd183d4e,0xbd75bc95,0xbb49bd80,
0x3cc4bd6d,0x3d803b49,0x3c953d75,0xbd4e3d18,0xbd55bd0e,0x3c79bd78,0x3d7fbbc9,0x3cdb3d67,0x3d80,0xbd713cac,0xbd22bd46,0x3d04bd5c,0x3d7b3c48,0x3c163d7d,0xbd623cf1,0xbd3ebd2c,
0xbd55bd0e,0x3cdbbd67,0x3d753c95,0xbc163d7d,0xbcc4bd6d,0x3d5cbd04,0x3d223d46,0xbd2c3d3e,0x3c48bd7b,0x3d803b49,0x3bc93d7f,0xbd783c79,0x3d35bd35,0x3d4e3d18,0xbcf13d62,0xbd71bcac,
0x3d7bbc48,0x3cac3d71,0xbd623cf1,0xbd18bd4e,0x3d6d3cc4,0xbc793d78,0xbd7fbbc9,0xbb49bd80,0x3d0e3d55,0xbd3e3d2c,0xbd46bd22,0x3d04bd5c,0x3d80,0xbd7d3c16,0xbc95bd75,0x3d67bcdb,
0xbd800000,0xbd80bb49,0xbd7fbbc9,0xbd7dbc16,0xbd7bbc48,0xbd78bc79,0xbd75bc95,0xbd71bcac,0xbd6dbcc4,0xbd67bcdb,0xbd62bcf1,0xbd5cbd04,0xbd55bd0e,0xbd4ebd18,0xbd46bd22,0xbd3ebd2c,
0xbd35bd35,0xbd2cbd3e,0xbd22bd46,0xbd18bd4e,0xbd0ebd55,0xbd04bd5c,0xbcf1bd62,0xbcdbbd67,0xbcc4bd6d,0xbcacbd71,0xbc95bd75,0xbc79bd78,0xbc48bd7b,0xbc16bd7d,0xbbc9bd7f,0xbb49bd80,
0xbd0ebd55,0xbcacbd71,0xbbc9bd7f,0x3c16bd7d,0xbd800000,0xbd78bc79,0xbd62bcf1,0xbd3ebd2c,0x3d7bbc48,0x3d803b49,0x3d753c95,0x3d5c3d04,0x3cc4bd6d,0x3d18bd4e,0x3d46bd22,0x3d67bcdb,
0xbc483d7b,0xbcdb3d67,0xbd223d46,0xbd4e3d18,0x3d353d35,0x3d043d5c,0x3c953d75,0x3b493d80,0xbd55bd0e,0xbd2cbd3e,0xbcf1bd62,0xbc79bd78,0xbd6d3cc4,0xbd7d3c16,0xbd7fbbc9,0xbd71bcac,
0x3d6d3cc4,0x3d2c3d3e,0x3c953d75,0xbc163d7d,0xbd0e3d55,0xbd5c3d04,0xbd7f3bc9,0xbd71bcac,0xbd800000,0xbd67bcdb,0xbd22bd46,0xbc79bd78,0x3c48bd7b,0x3d18bd4e,0x3d62bcf1,0x3d80bb49,
0x3cc43d6d,0xbb493d80,0xbcf13d62,0xbd4e3d18,0xbd7b3c48,0xbd78bc79,0xbd46bd22,0xbcdbbd67,0xbd35bd35,0xbcacbd71,0x3bc9bd7f,0x3d04bd5c,0x3d55bd0e,0x3d7dbc16,0x3d753c95,0x3d3e3d2c,
0xbc48bd7b,0x3cdbbd67,0x3d62bcf1,0x3d7d3c16,0xbcc43d6d,0xbd5c3d04,0xbd7fbbc9,0xbd3ebd2c,0x3d55bd0e,0x3d803b49,0x3d463d22,0x3c793d78,0xbd800000,0xbd4ebd18,0xbc95bd75,0x3cacbd71,
0xbd0e3d55,0xbd713cac,0xbd75bc95,0xbd18bd4e,0x3d6dbcc4,0x3d783c79,0x3d223d46,0x3b493d80,0xbd7bbc48,0xbd2cbd3e,0xbbc9bd7f,0x3d04bd5c,0x3d353d35,0x3c163d7d,0xbcf13d62,0xbd673cdb,
0xbd35bd35,0x3b49bd80,0x3d46bd22,0x3d7d3c16,0x3d0e3d55,0xbc793d78,0xbd623cf1,0xbd71bcac,0xbcc4bd6d,0x3cdbbd67,0x3d75bc95,0x3d5c3d04,0x3c483d7b,0xbd183d4e,0xbd7f3bc9,0xbd3ebd2c,
0xbd800000,0xbd2cbd3e,0x3bc9bd7f,0x3d4ebd18,0x3d7b3c48,0x3d043d5c,0xbc953d75,0xbd673cdb,0xbd6dbcc4,0xbcacbd71,0x3cf1bd62,0x3d78bc79,0x3d553d0e,0x3c163d7d,0xbd223d46,0xbd803b49,
0x3c48bd7b,0x3d71bcac,0x3d463d22,0xbc163d7d,0x3d353d35,0xbc793d78,0xbd753c95,0xbd3ebd2c,0x3d553d0e,0xbb493d80,0xbd623cf1,0xbd5cbd04,0xbd6d3cc4,0xbd4ebd18,0x3bc9bd7f,0x3d67bcdb,
0x3d0e3d55,0xbcdb3d67,0xbd7f3bc9,0xbd18bd4e,0xbd800000,0xbd04bd5c,0x3cf1bd62,0x3d80bb49,0xbd7b3c48,0xbd2cbd3e,0x3c95bd75,0x3d78bc79,0x3cc4bd6d,0x3d7dbc16,0x3d223d46,0xbcac3d71,
0x3cc43d6d,0xbd3e3d2c,0xbd62bcf1,0x3c16bd7d,0x3d7bbc48,0x3d043d5c,0xbd223d46,0xbd71bcac,0xbd35bd35,0x3cdbbd67,0x3d7f3bc9,0x3c793d78,0xbd553d0e,0xbd4ebd18,0x3c95bd75,0x3d80bb49,
0x3d6d3cc4,0xbb493d80,0xbd753c95,0xbd18bd4e,0x3d0ebd55,0x3d783c79,0x3bc93d7f,0xbd673cdb,0xbd800000,0xbcacbd71,0x3d46bd22,0x3d5c3d04,0xbc483d7b,0xbd7d3c16,0xbcf1bd62,0x3d2cbd3e,
0x3d0ebd55,0x3d673cdb,0xbc953d75,0xbd7dbc16,0x3d6dbcc4,0x3d043d5c,0xbd463d22,0xbd3ebd2c,0x3d7b3c48,0xbb493d80,0xbd7f3bc9,0xbc79bd78,0x3d353d35,0xbd183d4e,0xbd62bcf1,0x3cacbd71,
0x3c483d7b,0xbd713cac,0xbcf1bd62,0x3d4ebd18,0xbcc43d6d,0xbd78bc79,0x3bc9bd7f,0x3d80bb49,0xbd553d0e,0xbd2cbd3e,0x3d22bd46,0x3d5c3d04,0xbd800000,0xbc16bd7d,0x3d75bc95,0x3cdb3d67,
0x3d80,0xbd80bb49,0x3bc9bd7f,0x3d7d3c16,0xbc483d7b,0xbd78bc79,0x3c95bd75,0x3d713cac,0xbcc43d6d,0xbd67bcdb,0x3cf1bd62,0x3d5c3d04,0xbd0e3d55,0xbd4ebd18,0x3d22bd46,0x3d3e3d2c,
0xbd353d35,0xbd2cbd3e,0x3d46bd22,0x3d183d4e,0xbd553d0e,0xbd04bd5c,0x3d62bcf1,0x3cdb3d67,0xbd6d3cc4,0xbcacbd71,0x3d75bc95,0x3c793d78,0xbd7b3c48,0xbc16bd7d,0x3d7fbbc9,0x3b493d80,
0xbd553d0e,0xbcacbd71,0x3d7fbbc9,0xbc163d7d,0x3d80,0xbd78bc79,0x3cf1bd62,0x3d3e3d2c,0xbc48bd7b,0x3d803b49,0xbc953d75,0xbd5cbd04,0xbd6dbcc4,0x3d18bd4e,0x3d223d46,0xbd673cdb,
0x3d7b3c48,0xbcdb3d67,0xbd46bd22,0x3d4ebd18,0x3d35bd35,0x3d043d5c,0xbd753c95,0xbb49bd80,0xbd0e3d55,0xbd2cbd3e,0x3d62bcf1,0x3c793d78,0x3cc43d6d,0xbd7d3c16,0x3bc9bd7f,0x3d713cac,
0x3cc4bd6d,0x3d2c3d3e,0xbd753c95,0x3c16bd7d,0x3d553d0e,0xbd5c3d04,0xbbc9bd7f,0x3d713cac,0x3d80,0xbd67bcdb,0x3d46bd22,0x3c793d78,0xbd7bbc48,0x3d18bd4e,0x3cf13d62,0xbd803b49,
0x3d6dbcc4,0xbb493d80,0xbd62bcf1,0x3d4ebd18,0x3c483d7b,0xbd78bc79,0x3d22bd46,0x3cdb3d67,0xbd353d35,0xbcacbd71,0x3d7f3bc9,0xbd043d5c,0xbd0ebd55,0x3d7dbc16,0xbc953d75,0xbd3ebd2c,
0xbd7b3c48,0x3cdbbd67,0x3cf13d62,0xbd7dbc16,0x3d6d3cc4,0xbd5c3d04,0x3bc9bd7f,0x3d3e3d2c,0xbd0ebd55,0x3d803b49,0xbd223d46,0xbc79bd78,0x3d80,0xbd4ebd18,0x3d75bc95,0xbcac3d71,
0x3d553d0e,0xbd713cac,0x3c95bd75,0x3d183d4e,0xbcc4bd6d,0x3d783c79,0xbd463d22,0xbb49bd80,0xbc483d7b,0xbd2cbd3e,0x3d7fbbc9,0xbd043d5c,0x3d35bd35,0x3c163d7d,0xbd62bcf1,0x3d67bcdb,
0xbd353d35,0x3b49bd80,0x3d223d46,0xbd7dbc16,0x3d55bd0e,0xbc793d78,0xbcf1bd62,0x3d713cac,0xbd6d3cc4,0x3cdbbd67,0x3c953d75,0xbd5cbd04,0x3d7bbc48,0xbd183d4e,0xbbc9bd7f,0x3d3e3d2c,
0x3d80,0xbd2cbd3e,0x3d7f3bc9,0xbd4e3d18,0x3c48bd7b,0x3d043d5c,0xbd75bc95,0x3d67bcdb,0xbcc43d6d,0xbcacbd71,0x3d623cf1,0xbd783c79,0x3d0ebd55,0x3c163d7d,0xbd46bd22,0x3d80bb49,
0xbd7bbc48,0x3d71bcac,0xbd223d46,0x3c16bd7d,0x3d35bd35,0xbc793d78,0xbc95bd75,0x3d3e3d2c,0x3d0ebd55,0xbb493d80,0xbcf1bd62,0x3d5c3d04,0x3cc43d6d,0xbd4ebd18,0x3d7f3bc9,0xbd673cdb,
0x3d55bd0e,0xbcdb3d67,0xbbc9bd7f,0x3d183d4e,0x3d80,0xbd04bd5c,0x3d623cf1,0xbd803b49,0x3c483d7b,0xbd2cbd3e,0x3d753c95,0xbd783c79,0xbd6dbcc4,0x3d7dbc16,0xbd463d22,0x3cacbd71,
0x3d6dbcc4,0xbd3e3d2c,0x3cf1bd62,0xbc163d7d,0xbc48bd7b,0x3d043d5c,0xbd46bd22,0x3d713cac,0xbd353d35,0x3cdbbd67,0xbbc93d7f,0xbc79bd78,0x3d0e3d55,0xbd4ebd18,0x3d753c95,0xbd803b49,
0x3cc4bd6d,0xbb493d80,0xbc95bd75,0x3d183d4e,0xbd55bd0e,0x3d783c79,0xbd7f3bc9,0x3d67bcdb,0x3d80,0xbcacbd71,0x3d223d46,0xbd5cbd04,0x3d7b3c48,0xbd7d3c16,0x3d62bcf1,0xbd2c3d3e,
0xbd55bd0e,0x3d673cdb,0xbd75bc95,0x3d7d3c16,0xbcc4bd6d,0x3d043d5c,0xbd22bd46,0x3d3e3d2c,0x3c48bd7b,0xbb493d80,0xbbc9bd7f,0x3c793d78,0x3d35bd35,0xbd183d4e,0x3cf1bd62,0xbcac3d71,
0x3d7bbc48,0xbd713cac,0x3d62bcf1,0xbd4e3d18,0x3d6d3cc4,0xbd78bc79,0x3d7f3bc9,0xbd803b49,0x3d0e3d55,0xbd2cbd3e,0x3d463d22,0xbd5cbd04,0x3d80,0xbc16bd7d,0x3c953d75,0xbcdbbd67,
0xbd800000,0x3b49bd80,0x3d7f3bc9,0xbc163d7d,0xbd7bbc48,0x3c79bd78,0x3d753c95,0xbcac3d71,0xbd6dbcc4,0x3cdbbd67,0x3d623cf1,0xbd043d5c,0xbd55bd0e,0x3d18bd4e,0x3d463d22,0xbd2c3d3e,
0xbd35bd35,0x3d3ebd2c,0x3d223d46,0xbd4e3d18,0xbd0ebd55,0x3d5cbd04,0x3cf13d62,0xbd673cdb,0xbcc4bd6d,0x3d71bcac,0x3c953d75,0xbd783c79,0xbc48bd7b,0x3d7dbc16,0x3bc93d7f,0xbd803b49,
0xbd0ebd55,0x3d71bcac,0x3bc93d7f,0xbd7dbc16,0xbd800000,0x3c79bd78,0x3d623cf1,0xbd2c3d3e,0x3d7bbc48,0xbb493d80,0xbd75bc95,0x3d04bd5c,0x3cc4bd6d,0x3d4e3d18,0xbd463d22,0xbcdbbd67,
0xbc483d7b,0xbd67bcdb,0x3d22bd46,0x3d183d4e,0x3d353d35,0xbd5c3d04,0xbc95bd75,0x3d80bb49,0xbd55bd0e,0x3d3ebd2c,0x3cf13d62,0xbd783c79,0xbd6d3cc4,0xbc16bd7d,0x3d7f3bc9,0xbcac3d71,
0x3d6d3cc4,0xbd3e3d2c,0xbc95bd75,0x3d7d3c16,0xbd0e3d55,0xbd04bd5c,0x3d7fbbc9,0xbcac3d71,0xbd800000,0x3cdbbd67,0x3d223d46,0xbd783c79,0x3c48bd7b,0x3d4e3d18,0xbd623cf1,0xbb49bd80,
0x3cc43d6d,0xbd80bb49,0x3cf1bd62,0x3d183d4e,0xbd7b3c48,0x3c79bd78,0x3d463d22,0xbd673cdb,0xbd35bd35,0x3d71bcac,0xbbc93d7f,0xbd5cbd04,0x3d55bd0e,0x3c163d7d,0xbd75bc95,0x3d2cbd3e,
0xbc48bd7b,0x3d673cdb,0xbd623cf1,0x3c16bd7d,0xbcc43d6d,0xbd04bd5c,0x3d7f3bc9,0xbd2c3d3e,0x3d55bd0e,0xbb493d80,0xbd46bd22,0x3d78bc79,0xbd800000,0x3d18bd4e,0x3c953d75,0xbd71bcac,
0xbd0e3d55,0xbcacbd71,0x3d753c95,0xbd4e3d18,0x3d6dbcc4,0xbc793d78,0xbd22bd46,0x3d80bb49,0xbd7bbc48,0x3d3ebd2c,0x3bc93d7f,0xbd5cbd04,0x3d353d35,0xbd7d3c16,0x3cf1bd62,0x3cdb3d67,
0xbd35bd35,0x3d803b49,0xbd463d22,0x3c16bd7d,0x3d0e3d55,0xbd78bc79,0x3d62bcf1,0xbcac3d71,0xbcc4bd6d,0x3d673cdb,0xbd753c95,0x3d04bd5c,0x3c483d7b,0xbd4ebd18,0x3d7fbbc9,0xbd2c3d3e,
0xbd800000,0x3d3ebd2c,0xbbc93d7f,0xbd18bd4e,0x3d7b3c48,0xbd5c3d04,0x3c95bd75,0x3cdb3d67,0xbd6dbcc4,0x3d71bcac,0xbcf13d62,0xbc79bd78,0x3d553d0e,0xbd7d3c16,0x3d22bd46,0x3b493d80,
0x3c48bd7b,0x3cac3d71,0xbd46bd22,0x3d7d3c16,0x3d353d35,0xbd78bc79,0x3d75bc95,0xbd2c3d3e,0x3d553d0e,0xbd80bb49,0x3d62bcf1,0xbd043d5c,0xbd6d3cc4,0x3d18bd4e,0xbbc93d7f,0xbcdbbd67,
0x3d0e3d55,0xbd67bcdb,0x3d7fbbc9,0xbd4e3d18,0xbd800000,0x3d5cbd04,0xbcf13d62,0xbb49bd80,0xbd7b3c48,0x3d3ebd2c,0xbc953d75,0xbc79bd78,0x3cc4bd6d,0x3c163d7d,0xbd22bd46,0x3d713cac,
0x3cc43d6d,0xbd2cbd3e,0x3d623cf1,0xbd7dbc16,0x3d7bbc48,0xbd5c3d04,0x3d22bd46,0xbcac3d71,0xbd35bd35,0x3d673cdb,0xbd7fbbc9,0x3d78bc79,0xbd553d0e,0x3d18bd4e,0xbc953d75,0xbb49bd80,
0x3d6d3cc4,0xbd80bb49,0x3d75bc95,0xbd4e3d18,0x3d0ebd55,0xbc793d78,0xbbc9bd7f,0x3cdb3d67,0xbd800000,0x3d71bcac,0xbd463d22,0x3d04bd5c,0xbc483d7b,0xbc16bd7d,0x3cf13d62,0xbd3ebd2c,
0x3d0ebd55,0xbcdb3d67,0x3c95bd75,0xbc163d7d,0x3d6dbcc4,0xbd5c3d04,0x3d46bd22,0xbd2c3d3e,0x3d7b3c48,0xbd80bb49,0x3d7fbbc9,0xbd783c79,0x3d353d35,0xbd4ebd18,0x3d623cf1,0xbd71bcac,
0x3c483d7b,0xbcacbd71,0x3cf13d62,0xbd18bd4e,0xbcc43d6d,0x3c79bd78,0xbbc93d7f,0xbb49bd80,0xbd553d0e,0x3d3ebd2c,0xbd223d46,0x3d04bd5c,0xbd800000,0x3d7dbc16,0xbd753c95,0x3d67bcdb,
0x3d80,0x3b49bd80,0xbbc93d7f,0x3c16bd7d,0xbc483d7b,0x3c79bd78,0xbc953d75,0x3cacbd71,0xbcc43d6d,0x3cdbbd67,0xbcf13d62,0x3d04bd5c,0xbd0e3d55,0x3d18bd4e,0xbd223d46,0x3d2cbd3e,
0xbd353d35,0x3d3ebd2c,0xbd463d22,0x3d4ebd18,0xbd553d0e,0x3d5cbd04,0xbd623cf1,0x3d67bcdb,0xbd6d3cc4,0x3d71bcac,0xbd753c95,0x3d78bc79,0xbd7b3c48,0x3d7dbc16,0xbd7f3bc9,0x3d80bb49,
0xbd553d0e,0x3d71bcac,0xbd7f3bc9,0x3d7d3c16,0x3d80,0x3c79bd78,0xbcf13d62,0x3d2cbd3e,0xbc48bd7b,0xbb493d80,0x3c95bd75,0xbd043d5c,0xbd6dbcc4,0x3d4e3d18,0xbd22bd46,0x3cdb3d67,
0x3d7b3c48,0xbd67bcdb,0x3d463d22,0xbd18bd4e,0x3d35bd35,0xbd5c3d04,0x3d75bc95,0xbd803b49,0xbd0e3d55,0x3d3ebd2c,0xbd623cf1,0x3d78bc79,0x3cc43d6d,0xbc16bd7d,0xbbc93d7f,0x3cacbd71,
0x3cc4bd6d,0xbd3e3d2c,0x3d75bc95,0xbd7dbc16,0x3d553d0e,0xbd04bd5c,0x3bc93d7f,0x3cacbd71,0x3d80,0x3cdbbd67,0xbd463d22,0x3d78bc79,0xbd7bbc48,0x3d4e3d18,0xbcf1bd62,0x3b493d80,
0x3d6dbcc4,0xbd80bb49,0x3d623cf1,0xbd18bd4e,0x3c483d7b,0x3c79bd78,0xbd223d46,0x3d67bcdb,0xbd353d35,0x3d71bcac,0xbd7fbbc9,0x3d5c3d04,0xbd0ebd55,0x3c163d7d,0x3c95bd75,0xbd2c3d3e,
0xbd7b3c48,0x3d673cdb,0xbcf1bd62,0xbc163d7d,0x3d6d3cc4,0xbd04bd5c,0xbbc93d7f,0x3d2cbd3e,0xbd0ebd55,0xbb493d80,0x3d22bd46,0xbd783c79,0x3d80,0x3d18bd4e,0xbd753c95,0x3d713cac,
0x3d553d0e,0xbcacbd71,0xbc953d75,0x3d4ebd18,0xbcc4bd6d,0xbc793d78,0x3d46bd22,0xbd803b49,0xbc483d7b,0x3d3ebd2c,0xbd7f3bc9,0x3d5c3d04,0x3d35bd35,0xbd7d3c16,0x3d623cf1,0xbcdbbd67,
0xbd353d35,0x3d803b49,0xbd22bd46,0xbc163d7d,0x3d55bd0e,0xbd78bc79,0x3cf13d62,0x3cacbd71,0xbd6d3cc4,0x3d673cdb,0xbc95bd75,0xbd043d5c,0x3d7bbc48,0xbd4ebd18,0x3bc93d7f,0x3d2cbd3e,
0x3d80,0x3d3ebd2c,0xbd7fbbc9,0x3d183d4e,0x3c48bd7b,0xbd5c3d04,0x3d753c95,0xbcdbbd67,0xbcc43d6d,0x3d71bcac,0xbd62bcf1,0x3c793d78,0x3d0ebd55,0xbd7d3c16,0x3d463d22,0xbb49bd80,
0xbd7bbc48,0x3cac3d71,0x3d22bd46,0xbd7dbc16,0x3d35bd35,0xbd78bc79,0x3c953d75,0x3d2cbd3e,0x3d0ebd55,0xbd80bb49,0x3cf13d62,0x3d04bd5c,0x3cc43d6d,0x3d18bd4e,0xbd7fbbc9,0x3cdb3d67,
0x3d55bd0e,0xbd67bcdb,0x3bc93d7f,0x3d4ebd18,0x3d80,0x3d5cbd04,0xbd62bcf1,0x3b493d80,0x3c483d7b,0x3d3ebd2c,0xbd75bc95,0x3c793d78,0xbd6dbcc4,0x3c163d7d,0x3d46bd22,0xbd71bcac,
0x3d6dbcc4,0xbd2cbd3e,0xbcf13d62,0x3d7d3c16,0xbc48bd7b,0xbd5c3d04,0x3d463d22,0x3cacbd71,0xbd353d35,0x3d673cdb,0x3bc9bd7f,0xbd783c79,0x3d0e3d55,0x3d18bd4e,0xbd75bc95,0x3b493d80,
0x3cc4bd6d,0xbd80bb49,0x3c953d75,0x3d4ebd18,0xbd55bd0e,0xbc793d78,0x3d7fbbc9,0xbcdbbd67,0x3d80,0x3d71bcac,0xbd22bd46,0xbd043d5c,0x3d7b3c48,0xbc16bd7d,0xbd623cf1,0x3d3e3d2c,
0xbd55bd0e,0xbcdb3d67,0x3d753c95,0x3c16bd7d,0xbcc4bd6d,0xbd5c3d04,0x3d223d46,0x3d2cbd3e,0x3c48bd7b,0xbd80bb49,0x3bc93d7f,0x3d78bc79,0x3d35bd35,0xbd4ebd18,0xbcf13d62,0x3d713cac,
0x3d7bbc48,0xbcacbd71,0xbd623cf1,0x3d183d4e,0x3d6d3cc4,0x3c79bd78,0xbd7fbbc9,0x3b493d80,0x3d0e3d55,0x3d3ebd2c,0xbd46bd22,0xbd043d5c,0x3d80,0x3d7dbc16,0xbc95bd75,0xbd673cdb,
0xbd800000,0x3d803b49,0xbd7fbbc9,0x3d7d3c16,0xbd7bbc48,0x3d783c79,0xbd75bc95,0x3d713cac,0xbd6dbcc4,0x3d673cdb,0xbd62bcf1,0x3d5c3d04,0xbd55bd0e,0x3d4e3d18,0xbd46bd22,0x3d3e3d2c,
0xbd35bd35,0x3d2c3d3e,0xbd22bd46,0x3d183d4e,0xbd0ebd55,0x3d043d5c,0xbcf1bd62,0x3cdb3d67,0xbcc4bd6d,0x3cac3d71,0xbc95bd75,0x3c793d78,0xbc48bd7b,0x3c163d7d,0xbbc9bd7f,0x3b493d80,
0xbd0ebd55,0x3cac3d71,0xbbc9bd7f,0xbc163d7d,0xbd800000,0x3d783c79,0xbd62bcf1,0x3d3e3d2c,0x3d7bbc48,0xbd80bb49,0x3d753c95,0xbd5cbd04,0x3cc4bd6d,0xbd183d4e,0x3d46bd22,0xbd673cdb,
0xbc483d7b,0x3cdbbd67,0xbd223d46,0x3d4ebd18,0x3d353d35,0xbd04bd5c,0x3c953d75,0xbb49bd80,0xbd55bd0e,0x3d2c3d3e,0xbcf1bd62,0x3c793d78,0xbd6d3cc4,0x3d7dbc16,0xbd7fbbc9,0x3d713cac,
0x3d6d3cc4,0xbd2cbd3e,0x3c953d75,0x3c16bd7d,0xbd0e3d55,0x3d5cbd04,0xbd7f3bc9,0x3d713cac,0xbd800000,0x3d673cdb,0xbd22bd46,0x3c793d78,0x3c48bd7b,0xbd183d4e,0x3d62bcf1,0xbd803b49,
0x3cc43d6d,0x3b49bd80,0xbcf13d62,0x3d4ebd18,0xbd7b3c48,0x3d783c79,0xbd46bd22,0x3cdb3d67,0xbd35bd35,0x3cac3d71,0x3bc9bd7f,0xbd043d5c,0x3d55bd0e,0xbd7d3c16,0x3d753c95,0xbd3ebd2c,
0xbc48bd7b,0xbcdb3d67,0x3d62bcf1,0xbd7dbc16,0xbcc43d6d,0x3d5cbd04,0xbd7fbbc9,0x3d3e3d2c,0x3d55bd0e,0xbd80bb49,0x3d463d22,0xbc79bd78,0xbd800000,0x3d4e3d18,0xbc95bd75,0xbcac3d71,
0xbd0e3d55,0x3d71bcac,0xbd75bc95,0x3d183d4e,0x3d6dbcc4,0xbd78bc79,0x3d223d46,0xbb49bd80,0xbd7bbc48,0x3d2c3d3e,0xbbc9bd7f,0xbd043d5c,0x3d353d35,0xbc16bd7d,0xbcf13d62,0x3d67bcdb,
0xbd35bd35,0xbb493d80,0x3d46bd22,0xbd7dbc16,0x3d0e3d55,0x3c79bd78,0xbd623cf1,0x3d713cac,0xbcc4bd6d,0xbcdb3d67,0x3d75bc95,0xbd5cbd04,0x3c483d7b,0x3d18bd4e,0xbd7f3bc9,0x3d3e3d2c,
0xbd800000,0x3d2c3d3e,0x3bc9bd7f,0xbd4e3d18,0x3d7b3c48,0xbd04bd5c,0xbc953d75,0x3d67bcdb,0xbd6dbcc4,0x3cac3d71,0x3cf1bd62,0xbd783c79,0x3d553d0e,0xbc16bd7d,0xbd223d46,0x3d80bb49,
0x3c48bd7b,0xbd713cac,0x3d463d22,0x3c16bd7d,0x3d353d35,0x3c79bd78,0xbd753c95,0x3d3e3d2c,0x3d553d0e,0x3b49bd80,0xbd623cf1,0x3d5c3d04,0xbd6d3cc4,0x3d4e3d18,0x3bc9bd7f,0xbd673cdb,
0x3d0e3d55,0x3cdbbd67,0xbd7f3bc9,0x3d183d4e,0xbd800000,0x3d043d5c,0x3cf1bd62,0xbd803b49,0xbd7b3c48,0x3d2c3d3e,0x3c95bd75,0xbd783c79,0x3cc4bd6d,0xbd7d3c16,0x3d223d46,0x3cacbd71,
0x3cc43d6d,0x3d3ebd2c,0xbd62bcf1,0xbc163d7d,0x3d7bbc48,0xbd04bd5c,0xbd223d46,0x3d713cac,0xbd35bd35,0xbcdb3d67,0x3d7f3bc9,0xbc79bd78,0xbd553d0e,0x3d4e3d18,0x3c95bd75,0xbd803b49,
0x3d6d3cc4,0x3b49bd80,0xbd753c95,0x3d183d4e,0x3d0ebd55,0xbd78bc79,0x3bc93d7f,0x3d67bcdb,0xbd800000,0x3cac3d71,0x3d46bd22,0xbd5cbd04,0xbc483d7b,0x3d7dbc16,0xbcf1bd62,0xbd2c3d3e,
0x3d0ebd55,0xbd67bcdb,0xbc953d75,0x3d7d3c16,0x3d6dbcc4,0xbd04bd5c,0xbd463d22,0x3d3e3d2c,0x3d7b3c48,0x3b49bd80,0xbd7f3bc9,0x3c793d78,0x3d353d35,0x3d18bd4e,0xbd62bcf1,0xbcac3d71,
0x3c483d7b,0x3d71bcac,0xbcf1bd62,0xbd4e3d18,0xbcc43d6d,0x3d783c79,0x3bc9bd7f,0xbd803b49,0xbd553d0e,0x3d2c3d3e,0x3d22bd46,0xbd5cbd04,0xbd800000,0x3c163d7d,0x3d75bc95,0xbcdbbd67,
0x3d80,0x3d803b49,0x3bc9bd7f,0xbd7dbc16,0xbc483d7b,0x3d783c79,0x3c95bd75,0xbd71bcac,0xbcc43d6d,0x3d673cdb,0x3cf1bd62,0xbd5cbd04,0xbd0e3d55,0x3d4e3d18,0x3d22bd46,0xbd3ebd2c,
0xbd353d35,0x3d2c3d3e,0x3d46bd22,0xbd18bd4e,0xbd553d0e,0x3d043d5c,0x3d62bcf1,0xbcdbbd67,0xbd6d3cc4,0x3cac3d71,0x3d75bc95,0xbc79bd78,0xbd7b3c48,0x3c163d7d,0x3d7fbbc9,0xbb49bd80,
0xbd553d0e,0x3cac3d71,0x3d7fbbc9,0x3c16bd7d,0x3d80,0x3d783c79,0x3cf1bd62,0xbd3ebd2c,0xbc48bd7b,0xbd80bb49,0xbc953d75,0x3d5c3d04,0xbd6dbcc4,0xbd183d4e,0x3d223d46,0x3d67bcdb,
0x3d7b3c48,0x3cdbbd67,0xbd46bd22,0xbd4e3d18,0x3d35bd35,0xbd04bd5c,0xbd753c95,0x3b493d80,0xbd0e3d55,0x3d2c3d3e,0x3d62bcf1,0xbc79bd78,0x3cc43d6d,0x3d7dbc16,0x3bc9bd7f,0xbd71bcac,
0x3cc4bd6d,0xbd2cbd3e,0xbd753c95,0xbc163d7d,0x3d553d0e,0x3d5cbd04,0xbbc9bd7f,0xbd71bcac,0x3d80,0x3d673cdb,0x3d46bd22,0xbc79bd78,0xbd7bbc48,0xbd183d4e,0x3cf13d62,0x3d80bb49,
0x3d6dbcc4,0x3b49bd80,0xbd62bcf1,0xbd4e3d18,0x3c483d7b,0x3d783c79,0x3d22bd46,0xbcdbbd67,0xbd353d35,0x3cac3d71,0x3d7f3bc9,0x3d04bd5c,0xbd0ebd55,0xbd7d3c16,0xbc953d75,0x3d3e3d2c,
0xbd7b3c48,0xbcdb3d67,0x3cf13d62,0x3d7d3c16,0x3d6d3cc4,0x3d5cbd04,0x3bc9bd7f,0xbd3ebd2c,0xbd0ebd55,0xbd80bb49,0xbd223d46,0x3c793d78,0x3d80,0x3d4e3d18,0x3d75bc95,0x3cacbd71,
0x3d553d0e,0x3d71bcac,0x3c95bd75,0xbd18bd4e,0xbcc4bd6d,0xbd78bc79,0xbd463d22,0x3b493d80,0xbc483d7b,0x3d2c3d3e,0x3d7fbbc9,0x3d04bd5c,0x3d35bd35,0xbc16bd7d,0xbd62bcf1,0xbd673cdb,
0xbd353d35,0xbb493d80,0x3d223d46,0x3d7d3c16,0x3d55bd0e,0x3c79bd78,0xbcf1bd62,0xbd71bcac,0xbd6d3cc4,0xbcdb3d67,0x3c953d75,0x3d5c3d04,0x3d7bbc48,0x3d18bd4e,0xbbc9bd7f,0xbd3ebd2c,
0x3d80,0x3d2c3d3e,0x3d7f3bc9,0x3d4ebd18,0x3c48bd7b,0xbd04bd5c,0xbd75bc95,0xbd673cdb,0xbcc43d6d,0x3cac3d71,0x3d623cf1,0x3d78bc79,0x3d0ebd55,0xbc16bd7d,0xbd46bd22,0xbd803b49,
0xbd7bbc48,0xbd713cac,0xbd223d46,0xbc163d7d,0x3d35bd35,0x3c79bd78,0xbc95bd75,0xbd3ebd2c,0x3d0ebd55,0x3b49bd80,0xbcf1bd62,0xbd5cbd04,0x3cc43d6d,0x3d4e3d18,0x3d7f3bc9,0x3d67bcdb,
0x3d55bd0e,0x3cdbbd67,0xbbc9bd7f,0xbd18bd4e,0x3d80,0x3d043d5c,0x3d623cf1,0x3d80bb49,0x3c483d7b,0x3d2c3d3e,0x3d753c95,0x3d78bc79,0xbd6dbcc4,0xbd7d3c16,0xbd463d22,0xbcac3d71,
0x3d6dbcc4,0x3d3ebd2c,0x3cf1bd62,0x3c16bd7d,0xbc48bd7b,0xbd04bd5c,0xbd46bd22,0xbd71bcac,0xbd353d35,0xbcdb3d67,0xbbc93d7f,0x3c793d78,0x3d0e3d55,0x3d4e3d18,0x3d753c95,0x3d80bb49,
0x3cc4bd6d,0x3b49bd80,0xbc95bd75,0xbd18bd4e,0xbd55bd0e,0xbd78bc79,0xbd7f3bc9,0xbd673cdb,0x3d80,0x3cac3d71,0x3d223d46,0x3d5c3d04,0x3d7b3c48,0x3d7dbc16,0x3d62bcf1,0x3d2cbd3e,
0xbd55bd0e,0xbd67bcdb,0xbd75bc95,0xbd7dbc16,0xbcc4bd6d,0xbd04bd5c,0xbd22bd46,0xbd3ebd2c,0x3c48bd7b,0x3b49bd80,0xbbc9bd7f,0xbc79bd78,0x3d35bd35,0x3d18bd4e,0x3cf1bd62,0x3cacbd71,
0x3d7bbc48,0x3d71bcac,0x3d62bcf1,0x3d4ebd18,0x3d6d3cc4,0x3d783c79,0x3d7f3bc9,0x3d80bb49,0x3d0e3d55,0x3d2c3d3e,0x3d463d22,0x3d5c3d04,0x3d80,0x3c163d7d,0x3c953d75,0x3cdb3d67,
0xbd800000,0xbb493d80,0x3d7f3bc9,0x3c16bd7d,0xbd7bbc48,0xbc793d78,0x3d753c95,0x3cacbd71,0xbd6dbcc4,0xbcdb3d67,0x3d623cf1,0x3d04bd5c,0xbd55bd0e,0xbd183d4e,0x3d463d22,0x3d2cbd3e,
0xbd35bd35,0xbd3e3d2c,0x3d223d46,0x3d4ebd18,0xbd0ebd55,0xbd5c3d04,0x3cf13d62,0x3d67bcdb,0xbcc4bd6d,0xbd713cac,0x3c953d75,0x3d78bc79,0xbc48bd7b,0xbd7d3c16,0x3bc93d7f,0x3d80bb49,
0xbd0ebd55,0xbd713cac,0x3bc93d7f,0x3d7d3c16,0xbd800000,0xbc793d78,0x3d623cf1,0x3d2cbd3e,0x3d7bbc48,0x3b49bd80,0xbd75bc95,0xbd043d5c,0x3cc4bd6d,0xbd4ebd18,0xbd463d22,0x3cdb3d67,
0xbc483d7b,0x3d673cdb,0x3d22bd46,0xbd18bd4e,0x3d353d35,0x3d5cbd04,0xbc95bd75,0xbd803b49,0xbd55bd0e,0xbd3e3d2c,0x3cf13d62,0x3d78bc79,0xbd6d3cc4,0x3c163d7d,0x3d7f3bc9,0x3cacbd71,
0x3d6d3cc4,0x3d3ebd2c,0xbc95bd75,0xbd7dbc16,0xbd0e3d55,0x3d043d5c,0x3d7fbbc9,0x3cacbd71,0xbd800000,0xbcdb3d67,0x3d223d46,0x3d78bc79,0x3c48bd7b,0xbd4ebd18,0xbd623cf1,0x3b493d80,
0x3cc43d6d,0x3d803b49,0x3cf1bd62,0xbd18bd4e,0xbd7b3c48,0xbc793d78,0x3d463d22,0x3d67bcdb,0xbd35bd35,0xbd713cac,0xbbc93d7f,0x3d5c3d04,0x3d55bd0e,0xbc16bd7d,0xbd75bc95,0xbd2c3d3e,
0xbc48bd7b,0xbd67bcdb,0xbd623cf1,0xbc163d7d,0xbcc43d6d,0x3d043d5c,0x3d7f3bc9,0x3d2cbd3e,0x3d55bd0e,0x3b49bd80,0xbd46bd22,0xbd783c79,0xbd800000,0xbd183d4e,0x3c953d75,0x3d713cac,
0xbd0e3d55,0x3cac3d71,0x3d753c95,0x3d4ebd18,0x3d6dbcc4,0x3c79bd78,0xbd22bd46,0xbd803b49,0xbd7bbc48,0xbd3e3d2c,0x3bc93d7f,0x3d5c3d04,0x3d353d35,0x3d7dbc16,0x3cf1bd62,0xbcdbbd67,
0xbd35bd35,0xbd80bb49,0xbd463d22,0xbc163d7d,0x3d0e3d55,0x3d783c79,0x3d62bcf1,0x3cacbd71,0xbcc4bd6d,0xbd67bcdb,0xbd753c95,0xbd043d5c,0x3c483d7b,0x3d4e3d18,0x3d7fbbc9,0x3d2cbd3e,
0xbd800000,0xbd3e3d2c,0xbbc93d7f,0x3d183d4e,0x3d7b3c48,0x3d5cbd04,0x3c95bd75,0xbcdbbd67,0xbd6dbcc4,0xbd713cac,0xbcf13d62,0x3c793d78,0x3d553d0e,0x3d7dbc16,0x3d22bd46,0xbb49bd80,
0x3c48bd7b,0xbcacbd71,0xbd46bd22,0xbd7dbc16,0x3d353d35,0x3d783c79,0x3d75bc95,0x3d2cbd3e,0x3d553d0e,0x3d803b49,0x3d62bcf1,0x3d04bd5c,0xbd6d3cc4,0xbd183d4e,0xbbc93d7f,0x3cdb3d67,
0x3d0e3d55,0x3d673cdb,0x3d7fbbc9,0x3d4ebd18,0xbd800000,0xbd5c3d04,0xbcf13d62,0x3b493d80,0xbd7b3c48,0xbd3e3d2c,0xbc953d75,0x3c793d78,0x3cc4bd6d,0xbc16bd7d,0xbd22bd46,0xbd71bcac,
0x3cc43d6d,0x3d2c3d3e,0x3d623cf1,0x3d7d3c16,0x3d7bbc48,0x3d5cbd04,0x3d22bd46,0x3cacbd71,0xbd35bd35,0xbd67bcdb,0xbd7fbbc9,0xbd783c79,0xbd553d0e,0xbd183d4e,0xbc953d75,0x3b493d80,
0x3d6d3cc4,0x3d803b49,0x3d75bc95,0x3d4ebd18,0x3d0ebd55,0x3c79bd78,0xbbc9bd7f,0xbcdbbd67,0xbd800000,0xbd713cac,0xbd463d22,0xbd043d5c,0xbc483d7b,0x3c163d7d,0x3cf13d62,0x3d3e3d2c,
0x3d0ebd55,0x3cdbbd67,0x3c95bd75,0x3c16bd7d,0x3d6dbcc4,0x3d5cbd04,0x3d46bd22,0x3d2cbd3e,0x3d7b3c48,0x3d803b49,0x3d7fbbc9,0x3d78bc79,0x3d353d35,0x3d4e3d18,0x3d623cf1,0x3d713cac,
0x3c483d7b,0x3cac3d71,0x3cf13d62,0x3d183d4e,0xbcc43d6d,0xbc793d78,0xbbc93d7f,0x3b493d80,0xbd553d0e,0xbd3e3d2c,0xbd223d46,0xbd043d5c,0xbd800000,0xbd7d3c16,0xbd753c95,0xbd673cdb,
0x3d80,0xbbc93d7f,0xbc483d7b,0xbc953d75,0xbcc43d6d,0xbcf13d62,0xbd0e3d55,0xbd223d46,0xbd353d35,0xbd463d22,0xbd553d0e,0xbd623cf1,0xbd6d3cc4,0xbd753c95,0xbd7b3c48,0xbd7f3bc9,
0xbd800000,0xbd7fbbc9,0xbd7bbc48,0xbd75bc95,0xbd6dbcc4,0xbd62bcf1,0xbd55bd0e,0xbd46bd22,0xbd35bd35,0xbd22bd46,0xbd0ebd55,0xbcf1bd62,0xbcc4bd6d,0xbc95bd75,0xbc48bd7b,0xbbc9bd7f,
0xbd6d3cc4,0xbd7f3bc9,0xbd7bbc48,0xbd62bcf1,0x3d80,0xbc953d75,0xbd0e3d55,0xbd463d22,0x3cc4bd6d,0x3d22bd46,0x3d55bd0e,0x3d75bc95,0xbd35bd35,0xbcf1bd62,0xbc48bd7b,0x3bc9bd7f,
0x3cc43d6d,0x3bc93d7f,0xbc483d7b,0xbcf13d62,0x3d800000,0x3d753c95,0x3d553d0e,0x3d223d46,0xbd6dbcc4,0xbd46bd22,0xbd0ebd55,0xbc95bd75,0xbd353d35,0xbd623cf1,0xbd7b3c48,0xbd7fbbc9,
0x3d35bd35,0x3d75bc95,0x3d7b3c48,0x3d463d22,0x3cc43d6d,0xbbc93d7f,0xbd0e3d55,0xbd623cf1,0x3d80,0xbcf13d62,0xbd553d0e,0xbd7f3bc9,0xbd6dbcc4,0xbd22bd46,0xbc48bd7b,0x3c95bd75,
0x3d353d35,0x3c953d75,0xbc483d7b,0xbd223d46,0xbd6d3cc4,0xbd7fbbc9,0xbd55bd0e,0xbcf1bd62,0xbd800000,0xbd62bcf1,0xbd0ebd55,0xbbc9bd7f,0x3cc4bd6d,0x3d46bd22,0x3d7bbc48,0x3d753c95,
0xbd6dbcc4,0xbcf1bd62,0x3c48bd7b,0x3d46bd22,0x3d353d35,0x3bc93d7f,0xbd0e3d55,0xbd753c95,0xbcc4bd6d,0x3c95bd75,0x3d55bd0e,0x3d7f3bc9,0x3d80,0xbd223d46,0xbd7b3c48,0xbd62bcf1,
0xbcc43d6d,0xbd623cf1,0xbd7bbc48,0xbd22bd46,0x3d35bd35,0x3d7fbbc9,0x3d553d0e,0x3c953d75,0xbd6d3cc4,0xbd75bc95,0xbd0ebd55,0x3bc9bd7f,0x3d800000,0x3d463d22,0x3c483d7b,0xbcf13d62,
0xbd800000,0xbd22bd46,0x3c48bd7b,0x3d62bcf1,0x3d6d3cc4,0x3c953d75,0xbd0e3d55,0xbd7f3bc9,0xbd35bd35,0x3bc9bd7f,0x3d55bd0e,0x3d753c95,0x3cc43d6d,0xbcf13d62,0xbd7b3c48,0xbd46bd22,
0x3d80,0xbd463d22,0xbd7bbc48,0xbcf1bd62,0x3cc4bd6d,0x3d75bc95,0x3d553d0e,0x3bc93d7f,0xbd353d35,0xbd7fbbc9,0xbd0ebd55,0x3c95bd75,0x3d6dbcc4,0x3d623cf1,0x3c483d7b,0xbd223d46,
0xbcc4bd6d,0x3d22bd46,0x3d7b3c48,0x3c953d75,0x3d800000,0x3cf13d62,0xbd0e3d55,0xbd7fbbc9,0x3d6d3cc4,0x3bc93d7f,0xbd553d0e,0xbd62bcf1,0xbd353d35,0xbd75bc95,0xbc48bd7b,0x3d46bd22,
0x3d6dbcc4,0x3d463d22,0xbc483d7b,0xbd753c95,0x3d80,0xbd623cf1,0xbd55bd0e,0x3bc9bd7f,0xbcc43d6d,0xbd7f3bc9,0xbd0ebd55,0x3cf1bd62,0xbd35bd35,0x3c95bd75,0x3d7bbc48,0x3d223d46,
0x3d353d35,0xbcf13d62,0xbd7bbc48,0xbbc9bd7f,0x3d6dbcc4,0x3d223d46,0xbd0e3d55,0xbd75bc95,0xbd800000,0xbc95bd75,0x3d55bd0e,0x3d463d22,0xbcc43d6d,0xbd7fbbc9,0xbc48bd7b,0x3d62bcf1,
0x3d35bd35,0x3d623cf1,0xbc483d7b,0xbd7f3bc9,0xbcc4bd6d,0x3d46bd22,0x3d553d0e,0xbc953d75,0x3d80,0xbd753c95,0xbd0ebd55,0x3d22bd46,0x3d6d3cc4,0xbbc93d7f,0xbd7b3c48,0xbcf1bd62,
0x3cc4bd6d,0x3d753c95,0xbc483d7b,0xbd7fbbc9,0x3d35bd35,0x3d463d22,0xbd0e3d55,0xbd62bcf1,0x3d6dbcc4,0x3cf13d62,0xbd553d0e,0xbd22bd46,0x3d800000,0x3bc93d7f,0xbd7b3c48,0xbc95bd75,
0x3d6d3cc4,0xbc953d75,0xbd7bbc48,0x3bc9bd7f,0x3d353d35,0xbd223d46,0xbd55bd0e,0x3cf1bd62,0x3cc43d6d,0xbd623cf1,0xbd0ebd55,0x3d46bd22,0x3d80,0xbd7f3bc9,0xbc48bd7b,0x3d75bc95,
0xbd800000,0xbd7fbbc9,0xbd7bbc48,0xbd75bc95,0xbd6dbcc4,0xbd62bcf1,0xbd55bd0e,0xbd46bd22,0xbd35bd35,0xbd22bd46,0xbd0ebd55,0xbcf1bd62,0xbcc4bd6d,0xbc95bd75,0xbc48bd7b,0xbbc9bd7f,
0x8000bd80,0x3bc9bd7f,0x3c48bd7b,0x3c95bd75,0x3cc4bd6d,0x3cf1bd62,0x3d0ebd55,0x3d22bd46,0x3d35bd35,0x3d46bd22,0x3d55bd0e,0x3d62bcf1,0x3d6dbcc4,0x3d75bc95,0x3d7bbc48,0x3d7fbbc9,
0xbcc4bd6d,0xbbc9bd7f,0x3c48bd7b,0x3cf1bd62,0xbd800000,0xbd75bc95,0xbd55bd0e,0xbd22bd46,0x3d6d3cc4,0x3d463d22,0x3d0e3d55,0x3c953d75,0x3d35bd35,0x3d62bcf1,0x3d7bbc48,0x3d7f3bc9,
0xbd6d3cc4,0xbd7f3bc9,0xbd7bbc48,0xbd62bcf1,0x80003d80,0xbc953d75,0xbd0e3d55,0xbd463d22,0x3cc4bd6d,0x3d22bd46,0x3d55bd0e,0x3d75bc95,0xbd35bd35,0xbcf1bd62,0xbc48bd7b,0x3bc9bd7f,
0x3d353d35,0x3c953d75,0xbc483d7b,0xbd223d46,0xbd6d3cc4,0xbd7fbbc9,0xbd55bd0e,0xbcf1bd62,0xbd800000,0xbd62bcf1,0xbd0ebd55,0xbbc9bd7f,0x3cc4bd6d,0x3d46bd22,0x3d7bbc48,0x3d753c95,
0xbd353d35,0xbd753c95,0xbd7bbc48,0xbd46bd22,0xbcc4bd6d,0x3bc9bd7f,0x3d0ebd55,0x3d62bcf1,0x8000bd80,0x3cf1bd62,0x3d55bd0e,0x3d7fbbc9,0x3d6d3cc4,0x3d223d46,0x3c483d7b,0xbc953d75,
0x3cc4bd6d,0x3d62bcf1,0x3d7b3c48,0x3d223d46,0xbd353d35,0xbd7f3bc9,0xbd55bd0e,0xbc95bd75,0x3d6dbcc4,0x3d753c95,0x3d0e3d55,0xbbc93d7f,0xbd800000,0xbd46bd22,0xbc48bd7b,0x3cf1bd62,
0xbd6dbcc4,0xbcf1bd62,0x3c48bd7b,0x3d46bd22,0x3d353d35,0x3bc93d7f,0xbd0e3d55,0xbd753c95,0xbcc4bd6d,0x3c95bd75,0x3d55bd0e,0x3d7f3bc9,0x80003d80,0xbd223d46,0xbd7b3c48,0xbd62bcf1,
0x8000bd80,0x3d46bd22,0x3d7b3c48,0x3cf13d62,0xbcc43d6d,0xbd753c95,0xbd55bd0e,0xbbc9bd7f,0x3d35bd35,0x3d7f3bc9,0x3d0e3d55,0xbc953d75,0xbd6d3cc4,0xbd62bcf1,0xbc48bd7b,0x3d22bd46,
0xbd800000,0xbd22bd46,0x3c48bd7b,0x3d62bcf1,0x3d6d3cc4,0x3c953d75,0xbd0e3d55,0xbd7f3bc9,0xbd35bd35,0x3bc9bd7f,0x3d55bd0e,0x3d753c95,0x3cc43d6d,0xbcf13d62,0xbd7b3c48,0xbd46bd22,
0x3d6dbcc4,0x3d463d22,0xbc483d7b,0xbd753c95,0x80003d80,0xbd623cf1,0xbd55bd0e,0x3bc9bd7f,0xbcc43d6d,0xbd7f3bc9,0xbd0ebd55,0x3cf1bd62,0xbd35bd35,0x3c95bd75,0x3d7bbc48,0x3d223d46,
0x3cc43d6d,0xbd223d46,0xbd7bbc48,0xbc95bd75,0xbd800000,0xbcf1bd62,0x3d0ebd55,0x3d7f3bc9,0xbd6dbcc4,0xbbc9bd7f,0x3d55bd0e,0x3d623cf1,0x3d35bd35,0x3d753c95,0x3c483d7b,0xbd463d22,
0xbd353d35,0xbd62bcf1,0x3c48bd7b,0x3d7fbbc9,0x3cc43d6d,0xbd463d22,0xbd55bd0e,0x3c95bd75,0x8000bd80,0x3d75bc95,0x3d0e3d55,0xbd223d46,0xbd6dbcc4,0x3bc9bd7f,0x3d7bbc48,0x3cf13d62,
0x3d353d35,0xbcf13d62,0xbd7bbc48,0xbbc9bd7f,0x3d6dbcc4,0x3d223d46,0xbd0e3d55,0xbd75bc95,0xbd800000,0xbc95bd75,0x3d55bd0e,0x3d463d22,0xbcc43d6d,0xbd7fbbc9,0xbc48bd7b,0x3d62bcf1,
0x3d6d3cc4,0xbc953d75,0xbd7bbc48,0x3bc9bd7f,0x3d353d35,0xbd223d46,0xbd55bd0e,0x3cf1bd62,0x3cc43d6d,0xbd623cf1,0xbd0ebd55,0x3d46bd22,0x80003d80,0xbd7f3bc9,0xbc48bd7b,0x3d75bc95,
0xbcc43d6d,0xbd75bc95,0x3c48bd7b,0x3d7f3bc9,0xbd353d35,0xbd46bd22,0x3d0ebd55,0x3d623cf1,0xbd6d3cc4,0xbcf1bd62,0x3d55bd0e,0x3d223d46,0xbd800000,0xbbc9bd7f,0x3d7bbc48,0x3c953d75,
0x3d80,0xbd7fbbc9,0x3c48bd7b,0x3d753c95,0xbcc43d6d,0xbd62bcf1,0x3d0ebd55,0x3d463d22,0xbd353d35,0xbd22bd46,0x3d55bd0e,0x3cf13d62,0xbd6d3cc4,0xbc95bd75,0x3d7bbc48,0x3bc93d7f,
0xbd800000,0x3bc9bd7f,0x3d7b3c48,0xbc953d75,0xbd6dbcc4,0x3cf1bd62,0x3d553d0e,0xbd223d46,0xbd35bd35,0x3d46bd22,0x3d0e3d55,0xbd623cf1,0xbcc4bd6d,0x3d75bc95,0x3c483d7b,0xbd7f3bc9,
0xbd6d3cc4,0xbbc9bd7f,0x3d7b3c48,0xbcf13d62,0x3d80,0xbd75bc95,0x3d0ebd55,0x3d223d46,0x3cc4bd6d,0x3d463d22,0xbd553d0e,0xbc95bd75,0xbd35bd35,0x3d62bcf1,0x3c483d7b,0xbd7fbbc9,
0x3cc43d6d,0xbd7f3bc9,0x3c48bd7b,0x3d623cf1,0x3d800000,0xbc953d75,0xbd55bd0e,0x3d46bd22,0xbd6dbcc4,0x3d22bd46,0x3d0e3d55,0xbd753c95,0xbd353d35,0xbcf1bd62,0x3d7bbc48,0xbbc93d7f,
0x3d35bd35,0x3c953d75,0xbd7bbc48,0x3d22bd46,0x3cc43d6d,0xbd7fbbc9,0x3d0ebd55,0x3cf13d62,0x3d80,0xbd62bcf1,0x3d55bd0e,0x3bc93d7f,0xbd6dbcc4,0x3d46bd22,0x3c483d7b,0xbd75bc95,
0x3d353d35,0xbd753c95,0x3c48bd7b,0x3d463d22,0xbd6d3cc4,0x3bc9bd7f,0x3d553d0e,0xbd623cf1,0xbd800000,0x3cf1bd62,0x3d0e3d55,0xbd7f3bc9,0x3cc4bd6d,0x3d223d46,0xbd7b3c48,0x3c95bd75,
0xbd6dbcc4,0x3d62bcf1,0xbc483d7b,0xbd22bd46,0x3d353d35,0xbd7f3bc9,0x3d0ebd55,0x3c953d75,0xbcc4bd6d,0x3d753c95,0xbd553d0e,0x3bc9bd7f,0x3d80,0xbd46bd22,0x3d7bbc48,0xbcf13d62,
0xbcc43d6d,0xbcf1bd62,0x3d7b3c48,0xbd463d22,0x3d35bd35,0x3bc93d7f,0xbd55bd0e,0x3d75bc95,0xbd6d3cc4,0x3c95bd75,0x3d0e3d55,0xbd7fbbc9,0x3d800000,0xbd223d46,0xbc48bd7b,0x3d623cf1,
0xbd800000,0x3d46bd22,0xbc483d7b,0xbcf1bd62,0x3d6d3cc4,0xbd753c95,0x3d0ebd55,0x3bc93d7f,0xbd35bd35,0x3d7f3bc9,0xbd553d0e,0x3c95bd75,0x3cc43d6d,0xbd62bcf1,0x3d7bbc48,0xbd223d46,
0x3d80,0xbd22bd46,0x3d7b3c48,0xbd623cf1,0x3cc4bd6d,0x3c953d75,0xbd55bd0e,0x3d7fbbc9,0xbd353d35,0x3bc9bd7f,0x3d0e3d55,0xbd75bc95,0x3d6dbcc4,0xbcf13d62,0xbc48bd7b,0x3d463d22,
0xbcc4bd6d,0x3d463d22,0xbd7bbc48,0x3d75bc95,0x3d800000,0xbd623cf1,0x3d0ebd55,0xbbc93d7f,0x3d6d3cc4,0xbd7f3bc9,0x3d55bd0e,0xbcf13d62,0xbd353d35,0x3c95bd75,0x3c483d7b,0xbd22bd46,
0x3d6dbcc4,0xbd223d46,0x3c48bd7b,0x3c953d75,0x3d80,0xbcf1bd62,0x3d553d0e,0xbd7fbbc9,0xbcc43d6d,0xbbc9bd7f,0x3d0e3d55,0xbd62bcf1,0xbd35bd35,0x3d753c95,0xbd7b3c48,0x3d46bd22,
0x3d353d35,0xbd62bcf1,0x3d7b3c48,0xbd7f3bc9,0x3d6dbcc4,0xbd463d22,0x3d0ebd55,0xbc953d75,0xbd800000,0x3d75bc95,0xbd553d0e,0x3d22bd46,0xbcc43d6d,0x3bc9bd7f,0x3c483d7b,0xbcf1bd62,
0x3d35bd35,0xbcf13d62,0x3c48bd7b,0x3bc93d7f,0xbcc4bd6d,0x3d223d46,0xbd55bd0e,0x3d753c95,0x3d80,0xbc95bd75,0x3d0e3d55,0xbd46bd22,0x3d6d3cc4,0xbd7fbbc9,0x3d7bbc48,0xbd623cf1,
0x3cc4bd6d,0xbc953d75,0x3c48bd7b,0xbbc93d7f,0x3d35bd35,0xbd223d46,0x3d0ebd55,0xbcf13d62,0x3d6dbcc4,0xbd623cf1,0x3d55bd0e,0xbd463d22,0x3d800000,0xbd7f3bc9,0x3d7bbc48,0xbd753c95,
0x3d6d3cc4,0xbd75bc95,0x3d7b3c48,0xbd7fbbc9,0x3d353d35,0xbd46bd22,0x3d553d0e,0xbd62bcf1,0x3cc43d6d,0xbcf1bd62,0x3d0e3d55,0xbd22bd46,0x3d80,0xbbc9bd7f,0x3c483d7b,0xbc95bd75,
0xbd800000,0x3bc9bd7f,0x3d7b3c48,0xbc953d75,0xbd6dbcc4,0x3cf1bd62,0x3d553d0e,0xbd223d46,0xbd35bd35,0x3d46bd22,0x3d0e3d55,0xbd623cf1,0xbcc4bd6d,0x3d75bc95,0x3c483d7b,0xbd7f3bc9,
0x8000bd80,0x3d7f3bc9,0xbc483d7b,0xbd75bc95,0x3cc4bd6d,0x3d623cf1,0xbd0e3d55,0xbd46bd22,0x3d35bd35,0x3d223d46,0xbd553d0e,0xbcf1bd62,0x3d6dbcc4,0x3c953d75,0xbd7b3c48,0xbbc9bd7f,
0xbcc4bd6d,0x3d7fbbc9,0xbc483d7b,0xbd62bcf1,0xbd800000,0x3c95bd75,0x3d553d0e,0xbd463d22,0x3d6d3cc4,0xbd223d46,0xbd0ebd55,0x3d75bc95,0x3d35bd35,0x3cf13d62,0xbd7b3c48,0x3bc9bd7f,
0xbd6d3cc4,0xbbc9bd7f,0x3d7b3c48,0xbcf13d62,0x80003d80,0xbd75bc95,0x3d0ebd55,0x3d223d46,0x3cc4bd6d,0x3d463d22,0xbd553d0e,0xbc95bd75,0xbd35bd35,0x3d62bcf1,0x3c483d7b,0xbd7fbbc9,
0x3d353d35,0xbd753c95,0x3c48bd7b,0x3d463d22,0xbd6d3cc4,0x3bc9bd7f,0x3d553d0e,0xbd623cf1,0xbd800000,0x3cf1bd62,0x3d0e3d55,0xbd7f3bc9,0x3cc4bd6d,0x3d223d46,0xbd7b3c48,0x3c95bd75,
0xbd353d35,0xbc95bd75,0x3d7b3c48,0xbd223d46,0xbcc4bd6d,0x3d7f3bc9,0xbd0e3d55,0xbcf1bd62,0x8000bd80,0x3d623cf1,0xbd553d0e,0xbbc9bd7f,0x3d6d3cc4,0xbd463d22,0xbc48bd7b,0x3d753c95,
0x3cc4bd6d,0x3cf13d62,0xbd7bbc48,0x3d46bd22,0xbd353d35,0xbbc9bd7f,0x3d553d0e,0xbd753c95,0x3d6dbcc4,0xbc953d75,0xbd0ebd55,0x3d7f3bc9,0xbd800000,0x3d22bd46,0x3c483d7b,0xbd62bcf1,
0xbd6dbcc4,0x3d62bcf1,0xbc483d7b,0xbd22bd46,0x3d353d35,0xbd7f3bc9,0x3d0ebd55,0x3c953d75,0xbcc4bd6d,0x3d753c95,0xbd553d0e,0x3bc9bd7f,0x80003d80,0xbd46bd22,0x3d7bbc48,0xbcf13d62,
0x8000bd80,0x3d223d46,0xbd7bbc48,0x3d62bcf1,0xbcc43d6d,0xbc95bd75,0x3d553d0e,0xbd7f3bc9,0x3d35bd35,0xbbc93d7f,0xbd0ebd55,0x3d753c95,0xbd6d3cc4,0x3cf1bd62,0x3c483d7b,0xbd46bd22,
0xbd800000,0x3d46bd22,0xbc483d7b,0xbcf1bd62,0x3d6d3cc4,0xbd753c95,0x3d0ebd55,0x3bc93d7f,0xbd35bd35,0x3d7f3bc9,0xbd553d0e,0x3c95bd75,0x3cc43d6d,0xbd62bcf1,0x3d7bbc48,0xbd223d46,
0x3d6dbcc4,0xbd223d46,0x3c48bd7b,0x3c953d75,0x80003d80,0xbcf1bd62,0x3d553d0e,0xbd7fbbc9,0xbcc43d6d,0xbbc9bd7f,0x3d0e3d55,0xbd62bcf1,0xbd35bd35,0x3d753c95,0xbd7b3c48,0x3d46bd22,
0x3cc43d6d,0xbd46bd22,0x3d7b3c48,0xbd753c95,0xbd800000,0x3d62bcf1,0xbd0e3d55,0x3bc9bd7f,0xbd6dbcc4,0x3d7fbbc9,0xbd553d0e,0x3cf1bd62,0x3d35bd35,0xbc953d75,0xbc48bd7b,0x3d223d46,
0xbd353d35,0x3cf1bd62,0xbc483d7b,0xbbc9bd7f,0x3cc43d6d,0xbd22bd46,0x3d553d0e,0xbd75bc95,0x8000bd80,0x3c953d75,0xbd0ebd55,0x3d463d22,0xbd6dbcc4,0x3d7f3bc9,0xbd7b3c48,0x3d62bcf1,
0x3d353d35,0xbd62bcf1,0x3d7b3c48,0xbd7f3bc9,0x3d6dbcc4,0xbd463d22,0x3d0ebd55,0xbc953d75,0xbd800000,0x3d75bc95,0xbd553d0e,0x3d22bd46,0xbcc43d6d,0x3bc9bd7f,0x3c483d7b,0xbcf1bd62,
0x3d6d3cc4,0xbd75bc95,0x3d7b3c48,0xbd7fbbc9,0x3d353d35,0xbd46bd22,0x3d553d0e,0xbd62bcf1,0x3cc43d6d,0xbcf1bd62,0x3d0e3d55,0xbd22bd46,0x80003d80,0xbbc9bd7f,0x3c483d7b,0xbc95bd75,
0xbcc43d6d,0x3c95bd75,0xbc483d7b,0x3bc9bd7f,0xbd353d35,0x3d22bd46,0xbd0e3d55,0x3cf1bd62,0xbd6d3cc4,0x3d62bcf1,0xbd553d0e,0x3d46bd22,0xbd800000,0x3d7fbbc9,0xbd7b3c48,0x3d75bc95,
0x3d80,0x3bc9bd7f,0xbc483d7b,0x3c95bd75,0xbcc43d6d,0x3cf1bd62,0xbd0e3d55,0x3d22bd46,0xbd353d35,0x3d46bd22,0xbd553d0e,0x3d62bcf1,0xbd6d3cc4,0x3d75bc95,0xbd7b3c48,0x3d7fbbc9,
0xbd800000,0x3d7f3bc9,0xbd7bbc48,0x3d753c95,0xbd6dbcc4,0x3d623cf1,0xbd55bd0e,0x3d463d22,0xbd35bd35,0x3d223d46,0xbd0ebd55,0x3cf13d62,0xbcc4bd6d,0x3c953d75,0xbc48bd7b,0x3bc93d7f,
0xbd6d3cc4,0x3d7fbbc9,0xbd7bbc48,0x3d623cf1,0x3d80,0x3c95bd75,0xbd0e3d55,0x3d46bd22,0x3cc4bd6d,0xbd223d46,0x3d55bd0e,0xbd753c95,0xbd35bd35,0x3cf13d62,0xbc48bd7b,0xbbc93d7f,
0x3cc43d6d,0xbbc9bd7f,0xbc483d7b,0x3cf1bd62,0x3d800000,0xbd75bc95,0x3d553d0e,0xbd22bd46,0xbd6dbcc4,0x3d463d22,0xbd0ebd55,0x3c953d75,0xbd353d35,0x3d62bcf1,0xbd7b3c48,0x3d7f3bc9,
0x3d35bd35,0xbd753c95,0x3d7b3c48,0xbd46bd22,0x3cc43d6d,0x3bc9bd7f,0xbd0e3d55,0x3d62bcf1,0x3d80,0x3cf1bd62,0xbd553d0e,0x3d7fbbc9,0xbd6dbcc4,0x3d223d46,0xbc48bd7b,0xbc953d75,
0x3d353d35,0xbc95bd75,0xbc483d7b,0x3d22bd46,0xbd6d3cc4,0x3d7f3bc9,0xbd55bd0e,0x3cf13d62,0xbd800000,0x3d623cf1,0xbd0ebd55,0x3bc93d7f,0x3cc4bd6d,0xbd463d22,0x3d7bbc48,0xbd75bc95,
0xbd6dbcc4,0x3cf13d62,0x3c48bd7b,0xbd463d22,0x3d353d35,0xbbc9bd7f,0xbd0e3d55,0x3d75bc95,0xbcc4bd6d,0xbc953d75,0x3d55bd0e,0xbd7fbbc9,0x3d80,0x3d22bd46,0xbd7b3c48,0x3d623cf1,
0xbcc43d6d,0x3d62bcf1,0xbd7bbc48,0x3d223d46,0x3d35bd35,0xbd7f3bc9,0x3d553d0e,0xbc95bd75,0xbd6d3cc4,0x3d753c95,0xbd0ebd55,0xbbc93d7f,0x3d800000,0xbd46bd22,0x3c483d7b,0x3cf1bd62,
0xbd800000,0x3d223d46,0x3c48bd7b,0xbd623cf1,0x3d6d3cc4,0xbc95bd75,0xbd0e3d55,0x3d7fbbc9,0xbd35bd35,0xbbc93d7f,0x3d55bd0e,0xbd75bc95,0x3cc43d6d,0x3cf1bd62,0xbd7b3c48,0x3d463d22,
0x3d80,0x3d46bd22,0xbd7bbc48,0x3cf13d62,0x3cc4bd6d,0xbd753c95,0x3d553d0e,0xbbc9bd7f,0xbd353d35,0x3d7f3bc9,0xbd0ebd55,0xbc953d75,0x3d6dbcc4,0xbd62bcf1,0x3c483d7b,0x3d22bd46,
0xbcc4bd6d,0xbd223d46,0x3d7b3c48,0xbc95bd75,0x3d800000,0xbcf1bd62,0xbd0e3d55,0x3d7f3bc9,0x3d6d3cc4,0xbbc9bd7f,0xbd553d0e,0x3d623cf1,0xbd353d35,0x3d753c95,0xbc48bd7b,0xbd463d22,
0x3d6dbcc4,0xbd46bd22,0xbc483d7b,0x3d75bc95,0x3d80,0x3d62bcf1,0xbd55bd0e,0xbbc93d7f,0xbcc43d6d,0x3d7fbbc9,0xbd0ebd55,0xbcf13d62,0xbd35bd35,0xbc953d75,0x3d7bbc48,0xbd22bd46,
0x3d353d35,0x3cf1bd62,0xbd7bbc48,0x3bc93d7f,0x3d6dbcc4,0xbd22bd46,0xbd0e3d55,0x3d753c95,0xbd800000,0x3c953d75,0x3d55bd0e,0xbd46bd22,0xbcc43d6d,0x3d7f3bc9,0xbc48bd7b,0xbd623cf1,
0x3d35bd35,0xbd62bcf1,0xbc483d7b,0x3d7fbbc9,0xbcc4bd6d,0xbd463d22,0x3d553d0e,0x3c95bd75,0x3d80,0x3d75bc95,0xbd0ebd55,0xbd223d46,0x3d6d3cc4,0x3bc9bd7f,0xbd7b3c48,0x3cf13d62,
0x3cc4bd6d,0xbd75bc95,0xbc483d7b,0x3d7f3bc9,0x3d35bd35,0xbd46bd22,0xbd0e3d55,0x3d623cf1,0x3d6dbcc4,0xbcf1bd62,0xbd553d0e,0x3d223d46,0x3d800000,0xbbc9bd7f,0xbd7b3c48,0x3c953d75,
0x3d6d3cc4,0x3c95bd75,0xbd7bbc48,0xbbc93d7f,0x3d353d35,0x3d22bd46,0xbd55bd0e,0xbcf13d62,0x3cc43d6d,0x3d62bcf1,0xbd0ebd55,0xbd463d22,0x3d80,0x3d7fbbc9,0xbc48bd7b,0xbd753c95,
0xbd800000,0x3d7f3bc9,0xbd7bbc48,0x3d753c95,0xbd6dbcc4,0x3d623cf1,0xbd55bd0e,0x3d463d22,0xbd35bd35,0x3d223d46,0xbd0ebd55,0x3cf13d62,0xbcc4bd6d,0x3c953d75,0xbc48bd7b,0x3bc93d7f,
0x8000bd80,0xbbc93d7f,0x3c48bd7b,0xbc953d75,0x3cc4bd6d,0xbcf13d62,0x3d0ebd55,0xbd223d46,0x3d35bd35,0xbd463d22,0x3d55bd0e,0xbd623cf1,0x3d6dbcc4,0xbd753c95,0x3d7bbc48,0xbd7f3bc9,
0xbcc4bd6d,0x3bc93d7f,0x3c48bd7b,0xbcf13d62,0xbd800000,0x3d753c95,0xbd55bd0e,0x3d223d46,0x3d6d3cc4,0xbd46bd22,0x3d0e3d55,0xbc95bd75,0x3d35bd35,0xbd623cf1,0x3d7bbc48,0xbd7fbbc9,
0xbd6d3cc4,0x3d7fbbc9,0xbd7bbc48,0x3d623cf1,0x80003d80,0x3c95bd75,0xbd0e3d55,0x3d46bd22,0x3cc4bd6d,0xbd223d46,0x3d55bd0e,0xbd753c95,0xbd35bd35,0x3cf13d62,0xbc48bd7b,0xbbc93d7f,
0x3d353d35,0xbc95bd75,0xbc483d7b,0x3d22bd46,0xbd6d3cc4,0x3d7f3bc9,0xbd55bd0e,0x3cf13d62,0xbd800000,0x3d623cf1,0xbd0ebd55,0x3bc93d7f,0x3cc4bd6d,0xbd463d22,0x3d7bbc48,0xbd75bc95,
0xbd353d35,0x3d75bc95,0xbd7bbc48,0x3d463d22,0xbcc4bd6d,0xbbc93d7f,0x3d0ebd55,0xbd623cf1,0x8000bd80,0xbcf13d62,0x3d55bd0e,0xbd7f3bc9,0x3d6d3cc4,0xbd22bd46,0x3c483d7b,0x3c95bd75,
0x3cc4bd6d,0xbd623cf1,0x3d7b3c48,0xbd22bd46,0xbd353d35,0x3d7fbbc9,0xbd55bd0e,0x3c953d75,0x3d6dbcc4,0xbd75bc95,0x3d0e3d55,0x3bc9bd7f,0xbd800000,0x3d463d22,0xbc48bd7b,0xbcf13d62,
0xbd6dbcc4,0x3cf13d62,0x3c48bd7b,0xbd463d22,0x3d353d35,0xbbc9bd7f,0xbd0e3d55,0x3d75bc95,0xbcc4bd6d,0xbc953d75,0x3d55bd0e,0xbd7fbbc9,0x80003d80,0x3d22bd46,0xbd7b3c48,0x3d623cf1,
0x8000bd80,0xbd463d22,0x3d7b3c48,0xbcf1bd62,0xbcc43d6d,0x3d75bc95,0xbd55bd0e,0x3bc93d7f,0x3d35bd35,0xbd7fbbc9,0x3d0e3d55,0x3c95bd75,0xbd6d3cc4,0x3d623cf1,0xbc48bd7b,0xbd223d46,
0xbd800000,0x3d223d46,0x3c48bd7b,0xbd623cf1,0x3d6d3cc4,0xbc95bd75,0xbd0e3d55,0x3d7fbbc9,0xbd35bd35,0xbbc93d7f,0x3d55bd0e,0xbd75bc95,0x3cc43d6d,0x3cf1bd62,0xbd7b3c48,0x3d463d22,
0x3d6dbcc4,0xbd46bd22,0xbc483d7b,0x3d75bc95,0x80003d80,0x3d62bcf1,0xbd55bd0e,0xbbc93d7f,0xbcc43d6d,0x3d7fbbc9,0xbd0ebd55,0xbcf13d62,0xbd35bd35,0xbc953d75,0x3d7bbc48,0xbd22bd46,
0x3cc43d6d,0x3d22bd46,0xbd7bbc48,0x3c953d75,0xbd800000,0x3cf13d62,0x3d0ebd55,0xbd7fbbc9,0xbd6dbcc4,0x3bc93d7f,0x3d55bd0e,0xbd62bcf1,0x3d35bd35,0xbd75bc95,0x3c483d7b,0x3d46bd22,
0xbd353d35,0x3d623cf1,0x3c48bd7b,0xbd7f3bc9,0x3cc43d6d,0x3d46bd22,0xbd55bd0e,0xbc953d75,0x8000bd80,0xbd753c95,0x3d0e3d55,0x3d22bd46,0xbd6dbcc4,0xbbc93d7f,0x3d7bbc48,0xbcf1bd62,
0x3d353d35,0x3cf1bd62,0xbd7bbc48,0x3bc93d7f,0x3d6dbcc4,0xbd22bd46,0xbd0e3d55,0x3d753c95,0xbd800000,0x3c953d75,0x3d55bd0e,0xbd46bd22,0xbcc43d6d,0x3d7f3bc9,0xbc48bd7b,0xbd623cf1,
0x3d6d3cc4,0x3c95bd75,0xbd7bbc48,0xbbc93d7f,0x3d353d35,0x3d22bd46,0xbd55bd0e,0xbcf13d62,0x3cc43d6d,0x3d62bcf1,0xbd0ebd55,0xbd463d22,0x80003d80,0x3d7fbbc9,0xbc48bd7b,0xbd753c95,
0xbcc43d6d,0x3d753c95,0x3c48bd7b,0xbd7fbbc9,0xbd353d35,0x3d463d22,0x3d0ebd55,0xbd62bcf1,0xbd6d3cc4,0x3cf13d62,0x3d55bd0e,0xbd22bd46,0xbd800000,0x3bc93d7f,0x3d7bbc48,0xbc95bd75,
0x3d80,0x3d7f3bc9,0x3c48bd7b,0xbd75bc95,0xbcc43d6d,0x3d623cf1,0x3d0ebd55,0xbd46bd22,0xbd353d35,0x3d223d46,0x3d55bd0e,0xbcf1bd62,0xbd6d3cc4,0x3c953d75,0x3d7bbc48,0xbbc9bd7f,
0xbd800000,0xbbc93d7f,0x3d7b3c48,0x3c95bd75,0xbd6dbcc4,0xbcf13d62,0x3d553d0e,0x3d22bd46,0xbd35bd35,0xbd463d22,0x3d0e3d55,0x3d62bcf1,0xbcc4bd6d,0xbd753c95,0x3c483d7b,0x3d7fbbc9,
0xbd6d3cc4,0x3bc93d7f,0x3d7b3c48,0x3cf1bd62,0x3d80,0x3d753c95,0x3d0ebd55,0xbd22bd46,0x3cc4bd6d,0xbd46bd22,0xbd553d0e,0x3c953d75,0xbd35bd35,0xbd623cf1,0x3c483d7b,0x3d7f3bc9,
0x3cc43d6d,0x3d7fbbc9,0x3c48bd7b,0xbd62bcf1,0x3d800000,0x3c95bd75,0xbd55bd0e,0xbd463d22,0xbd6dbcc4,0xbd223d46,0x3d0e3d55,0x3d75bc95,0xbd353d35,0x3cf13d62,0x3d7bbc48,0x3bc9bd7f,
0x3d35bd35,0xbc95bd75,0xbd7bbc48,0xbd223d46,0x3cc43d6d,0x3d7f3bc9,0x3d0ebd55,0xbcf1bd62,0x3d80,0x3d623cf1,0x3d55bd0e,0xbbc9bd7f,0xbd6dbcc4,0xbd463d22,0x3c483d7b,0x3d753c95,
0x3d353d35,0x3d75bc95,0x3c48bd7b,0xbd46bd22,0xbd6d3cc4,0xbbc93d7f,0x3d553d0e,0x3d62bcf1,0xbd800000,0xbcf13d62,0x3d0e3d55,0x3d7fbbc9,0x3cc4bd6d,0xbd22bd46,0xbd7b3c48,0xbc953d75,
0xbd6dbcc4,0xbd623cf1,0xbc483d7b,0x3d223d46,0x3d353d35,0x3d7fbbc9,0x3d0ebd55,0xbc95bd75,0xbcc4bd6d,0xbd75bc95,0xbd553d0e,0xbbc93d7f,0x3d80,0x3d463d22,0x3d7bbc48,0x3cf1bd62,
0xbcc43d6d,0x3cf13d62,0x3d7b3c48,0x3d46bd22,0x3d35bd35,0xbbc9bd7f,0xbd55bd0e,0xbd753c95,0xbd6d3cc4,0xbc953d75,0x3d0e3d55,0x3d7f3bc9,0x3d800000,0x3d22bd46,0xbc48bd7b,0xbd62bcf1,
0xbd800000,0xbd463d22,0xbc483d7b,0x3cf13d62,0x3d6d3cc4,0x3d75bc95,0x3d0ebd55,0xbbc9bd7f,0xbd35bd35,0xbd7fbbc9,0xbd553d0e,0xbc953d75,0x3cc43d6d,0x3d623cf1,0x3d7bbc48,0x3d22bd46,
0x3d80,0x3d223d46,0x3d7b3c48,0x3d62bcf1,0x3cc4bd6d,0xbc95bd75,0xbd55bd0e,0xbd7f3bc9,0xbd353d35,0xbbc93d7f,0x3d0e3d55,0x3d753c95,0x3d6dbcc4,0x3cf1bd62,0xbc48bd7b,0xbd46bd22,
0xbcc4bd6d,0xbd46bd22,0xbd7bbc48,0xbd753c95,0x3d800000,0x3d62bcf1,0x3d0ebd55,0x3bc9bd7f,0x3d6d3cc4,0x3d7fbbc9,0x3d55bd0e,0x3cf1bd62,0xbd353d35,0xbc953d75,0x3c483d7b,0x3d223d46,
0x3d6dbcc4,0x3d22bd46,0x3c48bd7b,0xbc95bd75,0x3d80,0x3cf13d62,0x3d553d0e,0x3d7f3bc9,0xbcc43d6d,0x3bc93d7f,0x3d0e3d55,0x3d623cf1,0xbd35bd35,0xbd75bc95,0xbd7b3c48,0xbd463d22,
0x3d353d35,0x3d623cf1,0x3d7b3c48,0x3d7fbbc9,0x3d6dbcc4,0x3d46bd22,0x3d0ebd55,0x3c95bd75,0xbd800000,0xbd753c95,0xbd553d0e,0xbd223d46,0xbcc43d6d,0xbbc93d7f,0x3c483d7b,0x3cf13d62,
0x3d35bd35,0x3cf1bd62,0x3c48bd7b,0xbbc9bd7f,0xbcc4bd6d,0xbd22bd46,0xbd55bd0e,0xbd75bc95,0x3d80,0x3c953d75,0x3d0e3d55,0x3d463d22,0x3d6d3cc4,0x3d7f3bc9,0x3d7bbc48,0x3d62bcf1,
0x3cc4bd6d,0x3c95bd75,0x3c48bd7b,0x3bc9bd7f,0x3d35bd35,0x3d22bd46,0x3d0ebd55,0x3cf1bd62,0x3d6dbcc4,0x3d62bcf1,0x3d55bd0e,0x3d46bd22,0x3d800000,0x3d7fbbc9,0x3d7bbc48,0x3d75bc95,
0x3d6d3cc4,0x3d753c95,0x3d7b3c48,0x3d7f3bc9,0x3d353d35,0x3d463d22,0x3d553d0e,0x3d623cf1,0x3cc43d6d,0x3cf13d62,0x3d0e3d55,0x3d223d46,0x3d80,0x3bc93d7f,0x3c483d7b,0x3c953d75,
0xbd800000,0xbbc93d7f,0x3d7b3c48,0x3c95bd75,0xbd6dbcc4,0xbcf13d62,0x3d553d0e,0x3d22bd46,0xbd35bd35,0xbd463d22,0x3d0e3d55,0x3d62bcf1,0xbcc4bd6d,0xbd753c95,0x3c483d7b,0x3d7fbbc9,
0x8000bd80,0xbd7fbbc9,0xbc483d7b,0x3d753c95,0x3cc4bd6d,0xbd62bcf1,0xbd0e3d55,0x3d463d22,0x3d35bd35,0xbd22bd46,0xbd553d0e,0x3cf13d62,0x3d6dbcc4,0xbc95bd75,0xbd7b3c48,0x3bc93d7f,
0xbcc4bd6d,0xbd7f3bc9,0xbc483d7b,0x3d623cf1,0xbd800000,0xbc953d75,0x3d553d0e,0x3d46bd22,0x3d6d3cc4,0x3d22bd46,0xbd0ebd55,0xbd753c95,0x3d35bd35,0xbcf1bd62,0xbd7b3c48,0xbbc93d7f,
0xbd6d3cc4,0x3bc93d7f,0x3d7b3c48,0x3cf1bd62,0x80003d80,0x3d753c95,0x3d0ebd55,0xbd22bd46,0x3cc4bd6d,0xbd46bd22,0xbd553d0e,0x3c953d75,0xbd35bd35,0xbd623cf1,0x3c483d7b,0x3d7f3bc9,
0x3d353d35,0x3d75bc95,0x3c48bd7b,0xbd46bd22,0xbd6d3cc4,0xbbc93d7f,0x3d553d0e,0x3d62bcf1,0xbd800000,0xbcf13d62,0x3d0e3d55,0x3d7fbbc9,0x3cc4bd6d,0xbd22bd46,0xbd7b3c48,0xbc953d75,
0xbd353d35,0x3c953d75,0x3d7b3c48,0x3d22bd46,0xbcc4bd6d,0xbd7fbbc9,0xbd0e3d55,0x3cf13d62,0x8000bd80,0xbd62bcf1,0xbd553d0e,0x3bc93d7f,0x3d6d3cc4,0x3d46bd22,0xbc48bd7b,0xbd75bc95,
0x3cc4bd6d,0xbcf1bd62,0xbd7bbc48,0xbd463d22,0xbd353d35,0x3bc93d7f,0x3d553d0e,0x3d75bc95,0x3d6dbcc4,0x3c95bd75,0xbd0ebd55,0xbd7fbbc9,0xbd800000,0xbd223d46,0x3c483d7b,0x3d623cf1,
0xbd6dbcc4,0xbd623cf1,0xbc483d7b,0x3d223d46,0x3d353d35,0x3d7fbbc9,0x3d0ebd55,0xbc95bd75,0xbcc4bd6d,0xbd75bc95,0xbd553d0e,0xbbc93d7f,0x80003d80,0x3d463d22,0x3d7bbc48,0x3cf1bd62,
0x8000bd80,0xbd22bd46,0xbd7bbc48,0xbd623cf1,0xbcc43d6d,0x3c953d75,0x3d553d0e,0x3d7fbbc9,0x3d35bd35,0x3bc9bd7f,0xbd0ebd55,0xbd75bc95,0xbd6d3cc4,0xbcf13d62,0x3c483d7b,0x3d463d22,
0xbd800000,0xbd463d22,0xbc483d7b,0x3cf13d62,0x3d6d3cc4,0x3d75bc95,0x3d0ebd55,0xbbc9bd7f,0xbd35bd35,0xbd7fbbc9,0xbd553d0e,0xbc953d75,0x3cc43d6d,0x3d623cf1,0x3d7bbc48,0x3d22bd46,
0x3d6dbcc4,0x3d22bd46,0x3c48bd7b,0xbc95bd75,0x80003d80,0x3cf13d62,0x3d553d0e,0x3d7f3bc9,0xbcc43d6d,0x3bc93d7f,0x3d0e3d55,0x3d623cf1,0xbd35bd35,0xbd75bc95,0xbd7b3c48,0xbd463d22,
0x3cc43d6d,0x3d463d22,0x3d7b3c48,0x3d75bc95,0xbd800000,0xbd623cf1,0xbd0e3d55,0xbbc93d7f,0xbd6dbcc4,0xbd7f3bc9,0xbd553d0e,0xbcf13d62,0x3d35bd35,0x3c95bd75,0xbc48bd7b,0xbd22bd46,
0xbd353d35,0xbcf13d62,0xbc483d7b,0x3bc93d7f,0x3cc43d6d,0x3d223d46,0x3d553d0e,0x3d753c95,0x8000bd80,0xbc95bd75,0xbd0ebd55,0xbd46bd22,0xbd6dbcc4,0xbd7fbbc9,0xbd7b3c48,0xbd623cf1,
0x3d353d35,0x3d623cf1,0x3d7b3c48,0x3d7fbbc9,0x3d6dbcc4,0x3d46bd22,0x3d0ebd55,0x3c95bd75,0xbd800000,0xbd753c95,0xbd553d0e,0xbd223d46,0xbcc43d6d,0xbbc93d7f,0x3c483d7b,0x3cf13d62,
0x3d6d3cc4,0x3d753c95,0x3d7b3c48,0x3d7f3bc9,0x3d353d35,0x3d463d22,0x3d553d0e,0x3d623cf1,0x3cc43d6d,0x3cf13d62,0x3d0e3d55,0x3d223d46,0x80003d80,0x3bc93d7f,0x3c483d7b,0x3c953d75,
0xbcc43d6d,0xbc953d75,0xbc483d7b,0xbbc93d7f,0xbd353d35,0xbd223d46,0xbd0e3d55,0xbcf13d62,0xbd6d3cc4,0xbd623cf1,0xbd553d0e,0xbd463d22,0xbd800000,0xbd7f3bc9,0xbd7b3c48,0xbd753c95,
0x3d80,0xbc163d7d,0xbc953d75,0xbcdb3d67,0xbd0e3d55,0xbd2c3d3e,0xbd463d22,0xbd5c3d04,0xbd6d3cc4,0xbd783c79,0xbd7f3bc9,0xbd80bb49,0xbd7bbc48,0xbd71bcac,0xbd62bcf1,0xbd4ebd18,
0xbd35bd35,0xbd18bd4e,0xbcf1bd62,0xbcacbd71,0xbc48bd7b,0xbb49bd80,0x3bc9bd7f,0x3c79bd78,0x3cc4bd6d,0x3d04bd5c,0x3d22bd46,0x3d3ebd2c,0x3d55bd0e,0x3d67bcdb,0x3d75bc95,0x3d7dbc16,
0xbd7b3c48,0xbd7dbc16,0xbd62bcf1,0xbd2cbd3e,0x3d80,0xbcac3d71,0xbd223d46,0xbd5c3d04,0x3d55bd0e,0x3d78bc79,0x3d7f3bc9,0x3d673cdb,0xbcc4bd6d,0xbb49bd80,0x3c95bd75,0x3d18bd4e,
0xbd0e3d55,0xbd4e3d18,0xbd753c95,0xbd80bb49,0x3d353d35,0x3cdb3d67,0x3bc93d7f,0xbc793d78,0x3c48bd7b,0x3d04bd5c,0x3d46bd22,0x3d71bcac,0xbd6dbcc4,0xbd3ebd2c,0xbcf1bd62,0xbc16bd7d,
0x3d6dbcc4,0x3d7d3c16,0x3d463d22,0x3cac3d71,0xbc483d7b,0xbd2c3d3e,0xbd753c95,0xbd78bc79,0x3d80,0xbd043d5c,0xbd623cf1,0xbd80bb49,0xbd55bd0e,0xbcdbbd67,0x3bc9bd7f,0x3d18bd4e,
0xbcc43d6d,0xbd4e3d18,0xbd7f3bc9,0xbd67bcdb,0xbd0ebd55,0xbb49bd80,0x3cf1bd62,0x3d5cbd04,0xbd35bd35,0xbc79bd78,0x3c95bd75,0x3d3ebd2c,0x3d7bbc48,0x3d713cac,0x3d223d46,0x3c163d7d,
0xbd0ebd55,0x3c16bd7d,0x3d46bd22,0x3d803b49,0x3cc43d6d,0xbcac3d71,0xbd623cf1,0xbd78bc79,0xbc48bd7b,0x3d04bd5c,0x3d75bc95,0x3d673cdb,0x3d80,0xbd2c3d3e,0xbd7f3bc9,0xbd4ebd18,
0xbd7bbc48,0xbd18bd4e,0x3bc9bd7f,0x3d3ebd2c,0x3d6d3cc4,0x3cdb3d67,0xbc953d75,0xbd5c3d04,0xbd55bd0e,0xbc79bd78,0x3cf1bd62,0x3d71bcac,0x3d353d35,0x3b493d80,0xbd223d46,0xbd7d3c16,
0xbd35bd35,0x3c16bd7d,0x3d62bcf1,0x3d673cdb,0x3c483d7b,0xbd2c3d3e,0xbd7fbbc9,0xbd04bd5c,0x3cc4bd6d,0x3d78bc79,0x3d463d22,0xbb493d80,0xbd553d0e,0xbd71bcac,0xbc95bd75,0x3d18bd4e,
0x3d80,0xbd4e3d18,0xbd75bc95,0xbcacbd71,0x3d0ebd55,0x3d80bb49,0x3d223d46,0xbc793d78,0xbd6d3cc4,0xbd5cbd04,0xbbc9bd7f,0x3d3ebd2c,0x3d7b3c48,0x3cdb3d67,0xbcf13d62,0xbd7d3c16,
0x3d0ebd55,0x3d7d3c16,0x3c953d75,0xbd3e3d2c,0x3d353d35,0xbcac3d71,0xbd7f3bc9,0xbd04bd5c,0xbc483d7b,0xbd783c79,0xbd22bd46,0x3cdbbd67,0xbd6dbcc4,0xbb49bd80,0x3d62bcf1,0x3d4e3d18,
0x3d7bbc48,0x3d183d4e,0xbcf13d62,0xbd80bb49,0x3d80,0xbd673cdb,0xbd46bd22,0x3c79bd78,0xbd553d0e,0xbd5cbd04,0x3bc9bd7f,0x3d71bcac,0xbcc4bd6d,0x3d2cbd3e,0x3d753c95,0x3c163d7d,
0xbcc43d6d,0xbd7dbc16,0xbbc9bd7f,0x3d71bcac,0x3d0e3d55,0xbd2c3d3e,0xbd62bcf1,0x3c79bd78,0xbd35bd35,0x3d04bd5c,0x3d753c95,0xbb493d80,0xbd7b3c48,0xbcdbbd67,0x3d46bd22,0x3d4e3d18,
0x3d6dbcc4,0x3d183d4e,0xbd223d46,0xbd67bcdb,0x3c48bd7b,0x3d80bb49,0x3c953d75,0xbd5c3d04,0x3d80,0xbd783c79,0xbcf1bd62,0x3d3ebd2c,0x3d553d0e,0xbcac3d71,0xbd7fbbc9,0xbc16bd7d,
0x3d7b3c48,0xbc163d7d,0xbd7fbbc9,0x3b49bd80,0x3d6d3cc4,0xbcac3d71,0xbd75bc95,0x3c79bd78,0x3d553d0e,0xbd043d5c,0xbd62bcf1,0x3cdbbd67,0x3d353d35,0xbd2c3d3e,0xbd46bd22,0x3d18bd4e,
0x3d0e3d55,0xbd4e3d18,0xbd22bd46,0x3d3ebd2c,0x3cc43d6d,0xbd673cdb,0xbcf1bd62,0x3d5cbd04,0x3c483d7b,0xbd783c79,0xbc95bd75,0x3d71bcac,0x3d80,0xbd803b49,0xbbc9bd7f,0x3d7dbc16,
0xbd800000,0xbd7dbc16,0xbd75bc95,0xbd67bcdb,0xbd55bd0e,0xbd3ebd2c,0xbd22bd46,0xbd04bd5c,0xbcc4bd6d,0xbc79bd78,0xbbc9bd7f,0x3b49bd80,0x3c48bd7b,0x3cacbd71,0x3cf1bd62,0x3d18bd4e,
0x3d35bd35,0x3d4ebd18,0x3d62bcf1,0x3d71bcac,0x3d7bbc48,0x3d80bb49,0x3d7f3bc9,0x3d783c79,0x3d6d3cc4,0x3d5c3d04,0x3d463d22,0x3d2c3d3e,0x3d0e3d55,0x3cdb3d67,0x3c953d75,0x3c163d7d,
0xbc48bd7b,0x3c16bd7d,0x3cf1bd62,0x3d3ebd2c,0xbd800000,0xbd71bcac,0xbd46bd22,0xbd04bd5c,0x3d0e3d55,0x3c793d78,0xbbc93d7f,0xbcdb3d67,0x3d6dbcc4,0x3d80bb49,0x3d753c95,0x3d4e3d18,
0xbd55bd0e,0xbd18bd4e,0xbc95bd75,0x3b49bd80,0xbd353d35,0xbd673cdb,0xbd7f3bc9,0xbd78bc79,0x3d7b3c48,0x3d5c3d04,0x3d223d46,0x3cac3d71,0x3cc4bd6d,0x3d2cbd3e,0x3d62bcf1,0x3d7dbc16,
0x3cc43d6d,0xbc163d7d,0xbd223d46,0xbd713cac,0xbd7bbc48,0xbd3ebd2c,0xbc95bd75,0x3c79bd78,0xbd800000,0xbd5cbd04,0xbcf1bd62,0x3b49bd80,0x3d0ebd55,0x3d67bcdb,0x3d7f3bc9,0x3d4e3d18,
0xbd6dbcc4,0xbd18bd4e,0xbbc9bd7f,0x3cdbbd67,0x3d55bd0e,0x3d80bb49,0x3d623cf1,0x3d043d5c,0x3d35bd35,0x3d78bc79,0x3d753c95,0x3d2c3d3e,0x3c483d7b,0xbcac3d71,0xbd463d22,0xbd7d3c16,
0x3d55bd0e,0x3d7d3c16,0x3d223d46,0xbb493d80,0xbd6d3cc4,0xbd71bcac,0xbcf1bd62,0x3c79bd78,0x3d7bbc48,0x3d5c3d04,0x3c953d75,0xbcdb3d67,0xbd800000,0xbd3ebd2c,0xbbc9bd7f,0x3d18bd4e,
0x3c48bd7b,0x3d4ebd18,0x3d7f3bc9,0x3d2c3d3e,0xbcc43d6d,0xbd673cdb,0xbd75bc95,0xbd04bd5c,0x3d0ebd55,0x3d78bc79,0x3d623cf1,0x3cac3d71,0xbd353d35,0xbd803b49,0xbd46bd22,0xbc16bd7d,
0x3d35bd35,0x3d7d3c16,0x3cf13d62,0xbcdb3d67,0xbd7b3c48,0xbd3ebd2c,0x3bc9bd7f,0x3d5cbd04,0x3d6d3cc4,0x3c793d78,0xbd223d46,0xbd80bb49,0xbd0ebd55,0x3cacbd71,0x3d75bc95,0x3d4e3d18,
0xbd800000,0xbd18bd4e,0x3c95bd75,0x3d71bcac,0x3d553d0e,0x3b493d80,0xbd463d22,0xbd78bc79,0xbcc4bd6d,0x3d04bd5c,0x3d7fbbc9,0x3d2c3d3e,0xbc483d7b,0xbd673cdb,0xbd62bcf1,0xbc16bd7d,
0x3d553d0e,0xbc163d7d,0xbd753c95,0xbd2cbd3e,0xbd353d35,0xbd71bcac,0xbbc9bd7f,0x3d5cbd04,0xbd7bbc48,0xbc79bd78,0x3d46bd22,0x3d673cdb,0x3cc4bd6d,0x3d80bb49,0x3cf13d62,0xbd183d4e,
0x3c483d7b,0xbd4e3d18,0xbd62bcf1,0x3b49bd80,0xbd800000,0xbcdbbd67,0x3d22bd46,0x3d783c79,0xbd0ebd55,0x3d04bd5c,0x3d7f3bc9,0x3cac3d71,0x3d6dbcc4,0x3d3e3d2c,0xbc953d75,0xbd7d3c16,
0xbd6dbcc4,0x3c16bd7d,0x3d7fbbc9,0x3cac3d71,0xbd553d0e,0xbd3ebd2c,0x3cf1bd62,0x3d783c79,0x3d35bd35,0x3d5c3d04,0xbc953d75,0xbd80bb49,0xbc48bd7b,0x3d67bcdb,0x3d223d46,0xbd183d4e,
0x3cc43d6d,0xbd4e3d18,0xbd46bd22,0x3cdbbd67,0x3d7b3c48,0x3b493d80,0xbd753c95,0xbd04bd5c,0xbd800000,0xbc79bd78,0x3d62bcf1,0x3d2c3d3e,0xbd0e3d55,0xbd71bcac,0x3bc9bd7f,0x3d7dbc16,
0xbc483d7b,0xbd7dbc16,0x3bc9bd7f,0x3d803b49,0xbcc43d6d,0xbd71bcac,0x3c95bd75,0x3d783c79,0xbd0e3d55,0xbd5cbd04,0x3cf1bd62,0x3d673cdb,0xbd353d35,0xbd3ebd2c,0x3d22bd46,0x3d4e3d18,
0xbd553d0e,0xbd18bd4e,0x3d46bd22,0x3d2c3d3e,0xbd6d3cc4,0xbcdbbd67,0x3d62bcf1,0x3d043d5c,0xbd7b3c48,0xbc79bd78,0x3d75bc95,0x3cac3d71,0xbd800000,0xbb49bd80,0x3d7fbbc9,0x3c163d7d,
0x3d80,0xbd7dbc16,0x3c95bd75,0x3d673cdb,0xbd0e3d55,0xbd3ebd2c,0x3d46bd22,0x3d043d5c,0xbd6d3cc4,0xbc79bd78,0x3d7fbbc9,0xbb493d80,0xbd7bbc48,0x3cacbd71,0x3d623cf1,0xbd183d4e,
0xbd35bd35,0x3d4ebd18,0x3cf13d62,0xbd713cac,0xbc48bd7b,0x3d80bb49,0xbbc93d7f,0xbd78bc79,0x3cc4bd6d,0x3d5c3d04,0xbd223d46,0xbd2cbd3e,0x3d55bd0e,0x3cdb3d67,0xbd753c95,0xbc16bd7d,
0xbd7b3c48,0x3c16bd7d,0x3d623cf1,0xbd3e3d2c,0x3d80,0xbd71bcac,0x3d22bd46,0x3d043d5c,0x3d55bd0e,0x3c793d78,0xbd7fbbc9,0x3cdbbd67,0xbcc4bd6d,0x3d80bb49,0xbc953d75,0xbd4ebd18,
0xbd0e3d55,0xbd18bd4e,0x3d75bc95,0xbb493d80,0x3d353d35,0xbd673cdb,0xbbc9bd7f,0x3d783c79,0x3c48bd7b,0x3d5c3d04,0xbd463d22,0xbcacbd71,0xbd6dbcc4,0x3d2cbd3e,0x3cf13d62,0xbd7d3c16,
0x3d6dbcc4,0xbc163d7d,0xbd46bd22,0x3d71bcac,0xbc483d7b,0xbd3ebd2c,0x3d75bc95,0xbc793d78,0x3d80,0xbd5cbd04,0x3d62bcf1,0xbb493d80,0xbd55bd0e,0x3d67bcdb,0xbbc93d7f,0xbd4ebd18,
0xbcc43d6d,0xbd18bd4e,0x3d7fbbc9,0xbcdb3d67,0xbd0ebd55,0x3d80bb49,0xbcf13d62,0xbd04bd5c,0xbd35bd35,0x3d78bc79,0xbc953d75,0xbd2cbd3e,0x3d7bbc48,0xbcac3d71,0xbd22bd46,0x3d7dbc16,
0xbd0ebd55,0x3d7d3c16,0xbd463d22,0x3b49bd80,0x3cc43d6d,0xbd71bcac,0x3d62bcf1,0xbc793d78,0xbc48bd7b,0x3d5c3d04,0xbd753c95,0x3cdbbd67,0x3d80,0xbd3ebd2c,0x3d7fbbc9,0xbd183d4e,
0xbd7bbc48,0x3d4ebd18,0xbbc93d7f,0xbd2cbd3e,0x3d6d3cc4,0xbd673cdb,0x3c95bd75,0x3d043d5c,0xbd55bd0e,0x3d78bc79,0xbcf13d62,0xbcacbd71,0x3d353d35,0xbd803b49,0x3d22bd46,0x3c163d7d,
0xbd35bd35,0x3d7d3c16,0xbd623cf1,0x3cdbbd67,0x3c483d7b,0xbd3ebd2c,0x3d7f3bc9,0xbd5c3d04,0x3cc4bd6d,0x3c793d78,0xbd46bd22,0x3d803b49,0xbd553d0e,0x3cacbd71,0x3c953d75,0xbd4ebd18,
0x3d80,0xbd18bd4e,0x3d753c95,0xbd713cac,0x3d0ebd55,0x3b493d80,0xbd22bd46,0x3d783c79,0xbd6d3cc4,0x3d04bd5c,0x3bc93d7f,0xbd2cbd3e,0x3d7b3c48,0xbd673cdb,0x3cf1bd62,0x3c163d7d,
0x3d0ebd55,0xbc163d7d,0xbc95bd75,0x3d2c3d3e,0x3d353d35,0xbd71bcac,0x3d7fbbc9,0xbd5c3d04,0xbc483d7b,0xbc79bd78,0x3d223d46,0xbd67bcdb,0xbd6dbcc4,0x3d80bb49,0xbd623cf1,0x3d18bd4e,
0x3d7bbc48,0xbd4e3d18,0x3cf1bd62,0xbb493d80,0x3d80,0xbcdbbd67,0x3d463d22,0xbd78bc79,0xbd553d0e,0x3d04bd5c,0xbbc93d7f,0xbcacbd71,0xbcc4bd6d,0x3d3e3d2c,0xbd75bc95,0x3d7dbc16,
0xbcc43d6d,0x3c16bd7d,0x3bc93d7f,0xbcacbd71,0x3d0e3d55,0xbd3ebd2c,0x3d623cf1,0xbd78bc79,0xbd35bd35,0x3d5c3d04,0xbd75bc95,0x3d803b49,0xbd7b3c48,0x3d67bcdb,0xbd463d22,0x3d18bd4e,
0x3d6dbcc4,0xbd4e3d18,0x3d22bd46,0xbcdb3d67,0x3c48bd7b,0x3b493d80,0xbc95bd75,0x3d043d5c,0x3d80,0xbc79bd78,0x3cf13d62,0xbd2cbd3e,0x3d553d0e,0xbd71bcac,0x3d7f3bc9,0xbd7d3c16,
0x3d7b3c48,0xbd7dbc16,0x3d7f3bc9,0xbd80bb49,0x3d6d3cc4,0xbd71bcac,0x3d753c95,0xbd78bc79,0x3d553d0e,0xbd5cbd04,0x3d623cf1,0xbd67bcdb,0x3d353d35,0xbd3ebd2c,0x3d463d22,0xbd4ebd18,
0x3d0e3d55,0xbd18bd4e,0x3d223d46,0xbd2cbd3e,0x3cc43d6d,0xbcdbbd67,0x3cf13d62,0xbd04bd5c,0x3c483d7b,0xbc79bd78,0x3c953d75,0xbcacbd71,0x3d80,0xbb49bd80,0x3bc93d7f,0xbc16bd7d,
0xbd800000,0x3c16bd7d,0x3d753c95,0xbcdb3d67,0xbd55bd0e,0x3d2cbd3e,0x3d223d46,0xbd5c3d04,0xbcc4bd6d,0x3d78bc79,0x3bc93d7f,0xbd80bb49,0x3c48bd7b,0x3d713cac,0xbcf13d62,0xbd4ebd18,
0x3d35bd35,0x3d183d4e,0xbd623cf1,0xbcacbd71,0x3d7bbc48,0x3b493d80,0xbd7fbbc9,0x3c79bd78,0x3d6d3cc4,0xbd043d5c,0xbd46bd22,0x3d3ebd2c,0x3d0e3d55,0xbd673cdb,0xbc95bd75,0x3d7dbc16,
0xbc48bd7b,0x3d7d3c16,0xbcf13d62,0xbd2cbd3e,0xbd800000,0x3cacbd71,0x3d463d22,0xbd5c3d04,0x3d0e3d55,0xbd783c79,0x3bc9bd7f,0x3d673cdb,0x3d6dbcc4,0x3b493d80,0xbd75bc95,0x3d18bd4e,
0xbd55bd0e,0x3d4ebd18,0x3c953d75,0xbd80bb49,0xbd353d35,0xbcdbbd67,0x3d7fbbc9,0xbc793d78,0x3d7b3c48,0xbd043d5c,0xbd22bd46,0x3d71bcac,0x3cc4bd6d,0x3d3e3d2c,0xbd623cf1,0xbc16bd7d,
0x3cc43d6d,0xbd7dbc16,0x3d22bd46,0x3cac3d71,0xbd7bbc48,0x3d2cbd3e,0x3c953d75,0xbd78bc79,0xbd800000,0x3d04bd5c,0x3cf13d62,0xbd80bb49,0x3d0ebd55,0x3cdb3d67,0xbd7fbbc9,0x3d18bd4e,
0xbd6dbcc4,0x3d4ebd18,0x3bc93d7f,0xbd67bcdb,0x3d55bd0e,0x3b493d80,0xbd62bcf1,0x3d5cbd04,0x3d35bd35,0x3c793d78,0xbd75bc95,0x3d3ebd2c,0x3c483d7b,0xbd71bcac,0x3d46bd22,0x3c163d7d,
0x3d55bd0e,0xbc163d7d,0xbd22bd46,0x3d803b49,0xbd6d3cc4,0x3cacbd71,0x3cf13d62,0xbd78bc79,0x3d7bbc48,0xbd043d5c,0xbc95bd75,0x3d673cdb,0xbd800000,0x3d2cbd3e,0x3bc93d7f,0xbd4ebd18,
0x3c48bd7b,0x3d183d4e,0xbd7fbbc9,0x3d3ebd2c,0xbcc43d6d,0xbcdbbd67,0x3d753c95,0xbd5c3d04,0x3d0ebd55,0x3c793d78,0xbd62bcf1,0x3d71bcac,0xbd353d35,0xbb49bd80,0x3d463d22,0xbd7d3c16,
0x3d35bd35,0xbc163d7d,0xbcf1bd62,0x3d673cdb,0xbd7b3c48,0x3d2cbd3e,0xbbc93d7f,0xbd04bd5c,0x3d6d3cc4,0xbd783c79,0x3d22bd46,0xbb493d80,0xbd0ebd55,0x3d713cac,0xbd753c95,0x3d18bd4e,
0xbd800000,0x3d4ebd18,0xbc953d75,0xbcacbd71,0x3d553d0e,0xbd803b49,0x3d46bd22,0xbc793d78,0xbcc4bd6d,0x3d5c3d04,0xbd7f3bc9,0x3d3ebd2c,0xbc483d7b,0xbcdbbd67,0x3d623cf1,0xbd7d3c16,
0x3d553d0e,0xbd7dbc16,0x3d75bc95,0xbd3e3d2c,0xbd353d35,0x3cacbd71,0x3bc93d7f,0xbd04bd5c,0xbd7bbc48,0x3d78bc79,0xbd463d22,0x3cdbbd67,0x3cc4bd6d,0x3b493d80,0xbcf1bd62,0x3d4e3d18,
0x3c483d7b,0xbd18bd4e,0x3d623cf1,0xbd80bb49,0xbd800000,0x3d67bcdb,0xbd223d46,0x3c79bd78,0xbd0ebd55,0x3d5c3d04,0xbd7fbbc9,0x3d71bcac,0x3d6dbcc4,0xbd2c3d3e,0x3c95bd75,0x3c163d7d,
0xbd6dbcc4,0x3d7d3c16,0xbd7f3bc9,0x3d71bcac,0xbd553d0e,0x3d2cbd3e,0xbcf13d62,0x3c79bd78,0x3d35bd35,0xbd043d5c,0x3c95bd75,0xbb493d80,0xbc48bd7b,0x3cdb3d67,0xbd22bd46,0x3d4e3d18,
0x3cc43d6d,0xbd18bd4e,0x3d463d22,0xbd67bcdb,0x3d7b3c48,0xbd803b49,0x3d75bc95,0xbd5c3d04,0xbd800000,0x3d78bc79,0xbd623cf1,0x3d3ebd2c,0xbd0e3d55,0x3cacbd71,0xbbc93d7f,0xbc16bd7d,
0xbc483d7b,0x3c16bd7d,0xbbc93d7f,0x3b49bd80,0xbcc43d6d,0x3cacbd71,0xbc953d75,0x3c79bd78,0xbd0e3d55,0x3d04bd5c,0xbcf13d62,0x3cdbbd67,0xbd353d35,0x3d2cbd3e,0xbd223d46,0x3d18bd4e,
0xbd553d0e,0x3d4ebd18,0xbd463d22,0x3d3ebd2c,0xbd6d3cc4,0x3d67bcdb,0xbd623cf1,0x3d5cbd04,0xbd7b3c48,0x3d78bc79,0xbd753c95,0x3d71bcac,0xbd800000,0x3d80bb49,0xbd7f3bc9,0x3d7dbc16,
0x3d80,0x3c16bd7d,0xbc953d75,0x3cdbbd67,0xbd0e3d55,0x3d2cbd3e,0xbd463d22,0x3d5cbd04,0xbd6d3cc4,0x3d78bc79,0xbd7f3bc9,0x3d803b49,0xbd7bbc48,0x3d713cac,0xbd62bcf1,0x3d4e3d18,
0xbd35bd35,0x3d183d4e,0xbcf1bd62,0x3cac3d71,0xbc48bd7b,0x3b493d80,0x3bc9bd7f,0xbc793d78,0x3cc4bd6d,0xbd043d5c,0x3d22bd46,0xbd3e3d2c,0x3d55bd0e,0xbd673cdb,0x3d75bc95,0xbd7d3c16,
0xbd7b3c48,0x3d7d3c16,0xbd62bcf1,0x3d2c3d3e,0x3d80,0x3cacbd71,0xbd223d46,0x3d5cbd04,0x3d55bd0e,0xbd783c79,0x3d7f3bc9,0xbd67bcdb,0xbcc4bd6d,0x3b493d80,0x3c95bd75,0xbd183d4e,
0xbd0e3d55,0x3d4ebd18,0xbd753c95,0x3d803b49,0x3d353d35,0xbcdbbd67,0x3bc93d7f,0x3c79bd78,0x3c48bd7b,0xbd043d5c,0x3d46bd22,0xbd713cac,0xbd6dbcc4,0x3d3e3d2c,0xbcf1bd62,0x3c163d7d,
0x3d6dbcc4,0xbd7dbc16,0x3d463d22,0xbcacbd71,0xbc483d7b,0x3d2cbd3e,0xbd753c95,0x3d783c79,0x3d80,0x3d04bd5c,0xbd623cf1,0x3d803b49,0xbd55bd0e,0x3cdb3d67,0x3bc9bd7f,0xbd183d4e,
0xbcc43d6d,0x3d4ebd18,0xbd7f3bc9,0x3d673cdb,0xbd0ebd55,0x3b493d80,0x3cf1bd62,0xbd5c3d04,0xbd35bd35,0x3c793d78,0x3c95bd75,0xbd3e3d2c,0x3d7bbc48,0xbd71bcac,0x3d223d46,0xbc16bd7d,
0xbd0ebd55,0xbc163d7d,0x3d46bd22,0xbd80bb49,0x3cc43d6d,0x3cacbd71,0xbd623cf1,0x3d783c79,0xbc48bd7b,0xbd043d5c,0x3d75bc95,0xbd67bcdb,0x3d80,0x3d2cbd3e,0xbd7f3bc9,0x3d4e3d18,
0xbd7bbc48,0x3d183d4e,0x3bc9bd7f,0xbd3e3d2c,0x3d6d3cc4,0xbcdbbd67,0xbc953d75,0x3d5cbd04,0xbd55bd0e,0x3c793d78,0x3cf1bd62,0xbd713cac,0x3d353d35,0xbb49bd80,0xbd223d46,0x3d7dbc16,
0xbd35bd35,0xbc163d7d,0x3d62bcf1,0xbd67bcdb,0x3c483d7b,0x3d2cbd3e,0xbd7fbbc9,0x3d043d5c,0x3cc4bd6d,0xbd783c79,0x3d463d22,0x3b49bd80,0xbd553d0e,0x3d713cac,0xbc95bd75,0xbd183d4e,
0x3d80,0x3d4ebd18,0xbd75bc95,0x3cac3d71,0x3d0ebd55,0xbd803b49,0x3d223d46,0x3c79bd78,0xbd6d3cc4,0x3d5c3d04,0xbbc9bd7f,0xbd3e3d2c,0x3d7b3c48,0xbcdbbd67,0xbcf13d62,0x3d7dbc16,
0x3d0ebd55,0xbd7dbc16,0x3c953d75,0x3d3ebd2c,0x3d353d35,0x3cacbd71,0xbd7f3bc9,0x3d043d5c,0xbc483d7b,0x3d78bc79,0xbd22bd46,0xbcdb3d67,0xbd6dbcc4,0x3b493d80,0x3d62bcf1,0xbd4ebd18,
0x3d7bbc48,0xbd18bd4e,0xbcf13d62,0x3d803b49,0x3d80,0x3d67bcdb,0xbd46bd22,0xbc793d78,0xbd553d0e,0x3d5c3d04,0x3bc9bd7f,0xbd713cac,0xbcc4bd6d,0xbd2c3d3e,0x3d753c95,0xbc16bd7d,
0xbcc43d6d,0x3d7d3c16,0xbbc9bd7f,0xbd713cac,0x3d0e3d55,0x3d2cbd3e,0xbd62bcf1,0xbc793d78,0xbd35bd35,0xbd043d5c,0x3d753c95,0x3b49bd80,0xbd7b3c48,0x3cdb3d67,0x3d46bd22,0xbd4ebd18,
0x3d6dbcc4,0xbd18bd4e,0xbd223d46,0x3d673cdb,0x3c48bd7b,0xbd803b49,0x3c953d75,0x3d5cbd04,0x3d80,0x3d78bc79,0xbcf1bd62,0xbd3e3d2c,0x3d553d0e,0x3cacbd71,0xbd7fbbc9,0x3c163d7d,
0x3d7b3c48,0x3c16bd7d,0xbd7fbbc9,0xbb493d80,0x3d6d3cc4,0x3cacbd71,0xbd75bc95,0xbc793d78,0x3d553d0e,0x3d04bd5c,0xbd62bcf1,0xbcdb3d67,0x3d353d35,0x3d2cbd3e,0xbd46bd22,0xbd183d4e,
0x3d0e3d55,0x3d4ebd18,0xbd22bd46,0xbd3e3d2c,0x3cc43d6d,0x3d67bcdb,0xbcf1bd62,0xbd5c3d04,0x3c483d7b,0x3d78bc79,0xbc95bd75,0xbd713cac,0x3d80,0x3d80bb49,0xbbc9bd7f,0xbd7d3c16,
0xbd800000,0x3d7d3c16,0xbd75bc95,0x3d673cdb,0xbd55bd0e,0x3d3e3d2c,0xbd22bd46,0x3d043d5c,0xbcc4bd6d,0x3c793d78,0xbbc9bd7f,0xbb493d80,0x3c48bd7b,0xbcac3d71,0x3cf1bd62,0xbd183d4e,
0x3d35bd35,0xbd4e3d18,0x3d62bcf1,0xbd713cac,0x3d7bbc48,0xbd803b49,0x3d7f3bc9,0xbd78bc79,0x3d6d3cc4,0xbd5cbd04,0x3d463d22,0xbd2cbd3e,0x3d0e3d55,0xbcdbbd67,0x3c953d75,0xbc16bd7d,
0xbc48bd7b,0xbc163d7d,0x3cf1bd62,0xbd3e3d2c,0xbd800000,0x3d713cac,0xbd46bd22,0x3d043d5c,0x3d0e3d55,0xbc79bd78,0xbbc93d7f,0x3cdbbd67,0x3d6dbcc4,0xbd803b49,0x3d753c95,0xbd4ebd18,
0xbd55bd0e,0x3d183d4e,0xbc95bd75,0xbb493d80,0xbd353d35,0x3d67bcdb,0xbd7f3bc9,0x3d783c79,0x3d7b3c48,0xbd5cbd04,0x3d223d46,0xbcacbd71,0x3cc4bd6d,0xbd2c3d3e,0x3d62bcf1,0xbd7d3c16,
0x3cc43d6d,0x3c16bd7d,0xbd223d46,0x3d71bcac,0xbd7bbc48,0x3d3e3d2c,0xbc95bd75,0xbc793d78,0xbd800000,0x3d5c3d04,0xbcf1bd62,0xbb493d80,0x3d0ebd55,0xbd673cdb,0x3d7f3bc9,0xbd4ebd18,
0xbd6dbcc4,0x3d183d4e,0xbbc9bd7f,0xbcdb3d67,0x3d55bd0e,0xbd803b49,0x3d623cf1,0xbd04bd5c,0x3d35bd35,0xbd783c79,0x3d753c95,0xbd2cbd3e,0x3c483d7b,0x3cacbd71,0xbd463d22,0x3d7dbc16,
0x3d55bd0e,0xbd7dbc16,0x3d223d46,0x3b49bd80,0xbd6d3cc4,0x3d713cac,0xbcf1bd62,0xbc793d78,0x3d7bbc48,0xbd5cbd04,0x3c953d75,0x3cdbbd67,0xbd800000,0x3d3e3d2c,0xbbc9bd7f,0xbd183d4e,
0x3c48bd7b,0xbd4e3d18,0x3d7f3bc9,0xbd2cbd3e,0xbcc43d6d,0x3d67bcdb,0xbd75bc95,0x3d043d5c,0x3d0ebd55,0xbd783c79,0x3d623cf1,0xbcacbd71,0xbd353d35,0x3d80bb49,0xbd46bd22,0x3c163d7d,
0x3d35bd35,0xbd7dbc16,0x3cf13d62,0x3cdbbd67,0xbd7b3c48,0x3d3e3d2c,0x3bc9bd7f,0xbd5c3d04,0x3d6d3cc4,0xbc79bd78,0xbd223d46,0x3d803b49,0xbd0ebd55,0xbcac3d71,0x3d75bc95,0xbd4ebd18,
0xbd800000,0x3d183d4e,0x3c95bd75,0xbd713cac,0x3d553d0e,0xbb49bd80,0xbd463d22,0x3d783c79,0xbcc4bd6d,0xbd043d5c,0x3d7fbbc9,0xbd2cbd3e,0xbc483d7b,0x3d67bcdb,0xbd62bcf1,0x3c163d7d,
0x3d553d0e,0x3c16bd7d,0xbd753c95,0x3d2c3d3e,0xbd353d35,0x3d713cac,0xbbc9bd7f,0xbd5c3d04,0xbd7bbc48,0x3c793d78,0x3d46bd22,0xbd67bcdb,0x3cc4bd6d,0xbd803b49,0x3cf13d62,0x3d18bd4e,
0x3c483d7b,0x3d4ebd18,0xbd62bcf1,0xbb493d80,0xbd800000,0x3cdb3d67,0x3d22bd46,0xbd78bc79,0xbd0ebd55,0xbd043d5c,0x3d7f3bc9,0xbcacbd71,0x3d6dbcc4,0xbd3ebd2c,0xbc953d75,0x3d7dbc16,
0xbd6dbcc4,0xbc163d7d,0x3d7fbbc9,0xbcacbd71,0xbd553d0e,0x3d3e3d2c,0x3cf1bd62,0xbd78bc79,0x3d35bd35,0xbd5cbd04,0xbc953d75,0x3d803b49,0xbc48bd7b,0xbd673cdb,0x3d223d46,0x3d18bd4e,
0x3cc43d6d,0x3d4ebd18,0xbd46bd22,0xbcdb3d67,0x3d7b3c48,0xbb49bd80,0xbd753c95,0x3d043d5c,0xbd800000,0x3c793d78,0x3d62bcf1,0xbd2cbd3e,0xbd0e3d55,0x3d713cac,0x3bc9bd7f,0xbd7d3c16,
0xbc483d7b,0x3d7d3c16,0x3bc9bd7f,0xbd80bb49,0xbcc43d6d,0x3d713cac,0x3c95bd75,0xbd78bc79,0xbd0e3d55,0x3d5c3d04,0x3cf1bd62,0xbd67bcdb,0xbd353d35,0x3d3e3d2c,0x3d22bd46,0xbd4ebd18,
0xbd553d0e,0x3d183d4e,0x3d46bd22,0xbd2cbd3e,0xbd6d3cc4,0x3cdb3d67,0x3d62bcf1,0xbd04bd5c,0xbd7b3c48,0x3c793d78,0x3d75bc95,0xbcacbd71,0xbd800000,0x3b493d80,0x3d7fbbc9,0xbc16bd7d,
0x3d80,0x3d7d3c16,0x3c95bd75,0xbd67bcdb,0xbd0e3d55,0x3d3e3d2c,0x3d46bd22,0xbd04bd5c,0xbd6d3cc4,0x3c793d78,0x3d7fbbc9,0x3b49bd80,0xbd7bbc48,0xbcac3d71,0x3d623cf1,0x3d18bd4e,
0xbd35bd35,0xbd4e3d18,0x3cf13d62,0x3d71bcac,0xbc48bd7b,0xbd803b49,0xbbc93d7f,0x3d783c79,0x3cc4bd6d,0xbd5cbd04,0xbd223d46,0x3d2c3d3e,0x3d55bd0e,0xbcdbbd67,0xbd753c95,0x3c163d7d,
0xbd7b3c48,0xbc163d7d,0x3d623cf1,0x3d3ebd2c,0x3d80,0x3d713cac,0x3d22bd46,0xbd04bd5c,0x3d55bd0e,0xbc79bd78,0xbd7fbbc9,0xbcdb3d67,0xbcc4bd6d,0xbd803b49,0xbc953d75,0x3d4e3d18,
0xbd0e3d55,0x3d183d4e,0x3d75bc95,0x3b49bd80,0x3d353d35,0x3d67bcdb,0xbbc9bd7f,0xbd78bc79,0x3c48bd7b,0xbd5cbd04,0xbd463d22,0x3cac3d71,0xbd6dbcc4,0xbd2c3d3e,0x3cf13d62,0x3d7dbc16,
0x3d6dbcc4,0x3c16bd7d,0xbd46bd22,0xbd713cac,0xbc483d7b,0x3d3e3d2c,0x3d75bc95,0x3c79bd78,0x3d80,0x3d5c3d04,0x3d62bcf1,0x3b49bd80,0xbd55bd0e,0xbd673cdb,0xbbc93d7f,0x3d4e3d18,
0xbcc43d6d,0x3d183d4e,0x3d7fbbc9,0x3cdbbd67,0xbd0ebd55,0xbd803b49,0xbcf13d62,0x3d043d5c,0xbd35bd35,0xbd783c79,0xbc953d75,0x3d2c3d3e,0x3d7bbc48,0x3cacbd71,0xbd22bd46,0xbd7d3c16,
0xbd0ebd55,0xbd7dbc16,0xbd463d22,0xbb493d80,0x3cc43d6d,0x3d713cac,0x3d62bcf1,0x3c79bd78,0xbc48bd7b,0xbd5cbd04,0xbd753c95,0xbcdb3d67,0x3d80,0x3d3e3d2c,0x3d7fbbc9,0x3d18bd4e,
0xbd7bbc48,0xbd4e3d18,0xbbc93d7f,0x3d2c3d3e,0x3d6d3cc4,0x3d67bcdb,0x3c95bd75,0xbd04bd5c,0xbd55bd0e,0xbd783c79,0xbcf13d62,0x3cac3d71,0x3d353d35,0x3d80bb49,0x3d22bd46,0xbc16bd7d,
0xbd35bd35,0xbd7dbc16,0xbd623cf1,0xbcdb3d67,0x3c483d7b,0x3d3e3d2c,0x3d7f3bc9,0x3d5cbd04,0x3cc4bd6d,0xbc79bd78,0xbd46bd22,0xbd80bb49,0xbd553d0e,0xbcac3d71,0x3c953d75,0x3d4e3d18,
0x3d80,0x3d183d4e,0x3d753c95,0x3d71bcac,0x3d0ebd55,0xbb49bd80,0xbd22bd46,0xbd78bc79,0xbd6d3cc4,0xbd043d5c,0x3bc93d7f,0x3d2c3d3e,0x3d7b3c48,0x3d67bcdb,0x3cf1bd62,0xbc16bd7d,
0x3d0ebd55,0x3c16bd7d,0xbc95bd75,0xbd2cbd3e,0x3d353d35,0x3d713cac,0x3d7fbbc9,0x3d5cbd04,0xbc483d7b,0x3c793d78,0x3d223d46,0x3d673cdb,0xbd6dbcc4,0xbd803b49,0xbd623cf1,0xbd183d4e,
0x3d7bbc48,0x3d4ebd18,0x3cf1bd62,0x3b49bd80,0x3d80,0x3cdb3d67,0x3d463d22,0x3d783c79,0xbd553d0e,0xbd043d5c,0xbbc93d7f,0x3cac3d71,0xbcc4bd6d,0xbd3ebd2c,0xbd75bc95,0xbd7d3c16,
0xbcc43d6d,0xbc163d7d,0x3bc93d7f,0x3cac3d71,0x3d0e3d55,0x3d3e3d2c,0x3d623cf1,0x3d783c79,0xbd35bd35,0xbd5cbd04,0xbd75bc95,0xbd80bb49,0xbd7b3c48,0xbd673cdb,0xbd463d22,0xbd183d4e,
0x3d6dbcc4,0x3d4ebd18,0x3d22bd46,0x3cdbbd67,0x3c48bd7b,0xbb49bd80,0xbc95bd75,0xbd04bd5c,0x3d80,0x3c793d78,0x3cf13d62,0x3d2c3d3e,0x3d553d0e,0x3d713cac,0x3d7f3bc9,0x3d7dbc16,
0x3d7b3c48,0x3d7d3c16,0x3d7f3bc9,0x3d803b49,0x3d6d3cc4,0x3d713cac,0x3d753c95,0x3d783c79,0x3d553d0e,0x3d5c3d04,0x3d623cf1,0x3d673cdb,0x3d353d35,0x3d3e3d2c,0x3d463d22,0x3d4e3d18,
0x3d0e3d55,0x3d183d4e,0x3d223d46,0x3d2c3d3e,0x3cc43d6d,0x3cdb3d67,0x3cf13d62,0x3d043d5c,0x3c483d7b,0x3c793d78,0x3c953d75,0x3cac3d71,0x3d80,0x3b493d80,0x3bc93d7f,0x3c163d7d,
0xbd800000,0xbc163d7d,0x3d753c95,0x3cdbbd67,0xbd55bd0e,0xbd2c3d3e,0x3d223d46,0x3d5cbd04,0xbcc4bd6d,0xbd783c79,0x3bc93d7f,0x3d803b49,0x3c48bd7b,0xbd71bcac,0xbcf13d62,0x3d4e3d18,
0x3d35bd35,0xbd18bd4e,0xbd623cf1,0x3cac3d71,0x3d7bbc48,0xbb49bd80,0xbd7fbbc9,0xbc793d78,0x3d6d3cc4,0x3d04bd5c,0xbd46bd22,0xbd3e3d2c,0x3d0e3d55,0x3d67bcdb,0xbc95bd75,0xbd7d3c16,
0xbc48bd7b,0xbd7dbc16,0xbcf13d62,0x3d2c3d3e,0xbd800000,0xbcac3d71,0x3d463d22,0x3d5cbd04,0x3d0e3d55,0x3d78bc79,0x3bc9bd7f,0xbd67bcdb,0x3d6dbcc4,0xbb49bd80,0xbd75bc95,0xbd183d4e,
0xbd55bd0e,0xbd4e3d18,0x3c953d75,0x3d803b49,0xbd353d35,0x3cdb3d67,0x3d7fbbc9,0x3c79bd78,0x3d7b3c48,0x3d04bd5c,0xbd22bd46,0xbd713cac,0x3cc4bd6d,0xbd3ebd2c,0xbd623cf1,0x3c163d7d,
0x3cc43d6d,0x3d7d3c16,0x3d22bd46,0xbcacbd71,0xbd7bbc48,0xbd2c3d3e,0x3c953d75,0x3d783c79,0xbd800000,0xbd043d5c,0x3cf13d62,0x3d803b49,0x3d0ebd55,0xbcdbbd67,0xbd7fbbc9,0xbd183d4e,
0xbd6dbcc4,0xbd4e3d18,0x3bc93d7f,0x3d673cdb,0x3d55bd0e,0xbb49bd80,0xbd62bcf1,0xbd5c3d04,0x3d35bd35,0xbc79bd78,0xbd75bc95,0xbd3e3d2c,0x3c483d7b,0x3d713cac,0x3d46bd22,0xbc16bd7d,
0x3d55bd0e,0x3c16bd7d,0xbd22bd46,0xbd80bb49,0xbd6d3cc4,0xbcac3d71,0x3cf13d62,0x3d783c79,0x3d7bbc48,0x3d04bd5c,0xbc95bd75,0xbd67bcdb,0xbd800000,0xbd2c3d3e,0x3bc93d7f,0x3d4e3d18,
0x3c48bd7b,0xbd18bd4e,0xbd7fbbc9,0xbd3e3d2c,0xbcc43d6d,0x3cdb3d67,0x3d753c95,0x3d5cbd04,0x3d0ebd55,0xbc79bd78,0xbd62bcf1,0xbd713cac,0xbd353d35,0x3b493d80,0x3d463d22,0x3d7dbc16,
0x3d35bd35,0x3c16bd7d,0xbcf1bd62,0xbd67bcdb,0xbd7b3c48,0xbd2c3d3e,0xbbc93d7f,0x3d043d5c,0x3d6d3cc4,0x3d78bc79,0x3d22bd46,0x3b49bd80,0xbd0ebd55,0xbd71bcac,0xbd753c95,0xbd183d4e,
0xbd800000,0xbd4e3d18,0xbc953d75,0x3cac3d71,0x3d553d0e,0x3d80bb49,0x3d46bd22,0x3c79bd78,0xbcc4bd6d,0xbd5cbd04,0xbd7f3bc9,0xbd3e3d2c,0xbc483d7b,0x3cdb3d67,0x3d623cf1,0x3d7dbc16,
0x3d553d0e,0x3d7d3c16,0x3d75bc95,0x3d3ebd2c,0xbd353d35,0xbcac3d71,0x3bc93d7f,0x3d043d5c,0xbd7bbc48,0xbd783c79,0xbd463d22,0xbcdb3d67,0x3cc4bd6d,0xbb49bd80,0xbcf1bd62,0xbd4ebd18,
0x3c483d7b,0x3d183d4e,0x3d623cf1,0x3d803b49,0xbd800000,0xbd673cdb,0xbd223d46,0xbc793d78,0xbd0ebd55,0xbd5cbd04,0xbd7fbbc9,0xbd713cac,0x3d6dbcc4,0x3d2cbd3e,0x3c95bd75,0xbc16bd7d,
0xbd6dbcc4,0xbd7dbc16,0xbd7f3bc9,0xbd713cac,0xbd553d0e,0xbd2c3d3e,0xbcf13d62,0xbc793d78,0x3d35bd35,0x3d04bd5c,0x3c95bd75,0x3b49bd80,0xbc48bd7b,0xbcdbbd67,0xbd22bd46,0xbd4ebd18,
0x3cc43d6d,0x3d183d4e,0x3d463d22,0x3d673cdb,0x3d7b3c48,0x3d80bb49,0x3d75bc95,0x3d5cbd04,0xbd800000,0xbd783c79,0xbd623cf1,0xbd3e3d2c,0xbd0e3d55,0xbcac3d71,0xbbc93d7f,0x3c163d7d,
0xbc483d7b,0xbc163d7d,0xbbc93d7f,0xbb493d80,0xbcc43d6d,0xbcac3d71,0xbc953d75,0xbc793d78,0xbd0e3d55,0xbd043d5c,0xbcf13d62,0xbcdb3d67,0xbd353d35,0xbd2c3d3e,0xbd223d46,0xbd183d4e,
0xbd553d0e,0xbd4e3d18,0xbd463d22,0xbd3e3d2c,0xbd6d3cc4,0xbd673cdb,0xbd623cf1,0xbd5c3d04,0xbd7b3c48,0xbd783c79,0xbd753c95,0xbd713cac,0xbd800000,0xbd803b49,0xbd7f3bc9,0xbd7d3c16,
0x3f003f00,0xbf003f00,0x3f003f00,0xbf003f00,0x3f003f00,0xbf003f00,0x3f003f00,0xbf003f00,0x3f003f00,0xbf003f00,0x3f003f00,0xbf003f00,0x3f003f00,0xbf003f00,0x3f003f00,0xbf003f00,
0x3eff3f00,0xbd490000,0x3ea23eb5,0xbec6beb5,0x3ef53efb,0xbe15bdc8,0x3e713e8e,0xbee2bed5,0x3ee23eed,0xbe71be44,0x3e153e44,0xbef5beed,0x3ec63ed5,0xbea2be8e,0x3d493dc8,0xbeffbefb,
0x3efb3f00,0xbdc80000,0xbdc80000,0xbefbbf00,0x3ed53eed,0xbe8ebe44,0xbe8ebe44,0xbed5beed,0x3e8e3eb5,0xbed5beb5,0xbed5beb5,0xbe8ebeb5,0x3dc83e44,0xbefbbeed,0xbefbbeed,0xbdc8be44,
0x3ef53f00,0xbe150000,0xbee2beb5,0xbe71beb5,0x3ea23ed5,0xbec6be8e,0xbeffbefb,0x3d49bdc8,0x3d493e44,0xbeffbeed,0xbec6beed,0x3ea23e44,0xbe71bdc8,0xbee2befb,0xbe15be8e,0x3ef53ed5,
0x3eed3f00,0xbe440000,0xbeedbf00,0x3e440000,0x3e443eb5,0xbeedbeb5,0xbe44beb5,0x3eed3eb5,0xbe440000,0xbeedbf00,0x3e440000,0x3eed3f00,0xbeedbeb5,0xbe44beb5,0x3eed3eb5,0x3e443eb5,
0x3ee23f00,0xbe710000,0xbe15beb5,0x3ef53eb5,0x3d493e8e,0xbeffbed5,0x3ea23dc8,0x3ec63efb,0xbec6be44,0xbea2beed,0x3eff3eed,0xbd493e44,0xbef5befb,0x3e15bdc8,0x3e713ed5,0xbee2be8e,
0x3ed53f00,0xbe8e0000,0x3e8e0000,0x3ed53f00,0xbdc83e44,0xbefbbeed,0x3efb3eed,0xbdc83e44,0xbefbbeb5,0xbdc8beb5,0x3dc83eb5,0xbefbbeb5,0xbe8ebeed,0x3ed53e44,0xbed5be44,0xbe8ebeed,
0x3ec63f00,0xbea20000,0x3eff3eb5,0x3d493eb5,0xbe713dc8,0xbee2befb,0x3e153ed5,0xbef5be8e,0xbef5beed,0x3e15be44,0xbee2be44,0xbe71beed,0x3d49be8e,0x3eff3ed5,0xbea2befb,0x3ec63dc8,
0x3f00,0xbf000000,0x3f00,0xbf000000,0xbf00,0x3f000000,0xbf00,0x3f000000,0x3f00,0xbf000000,0x3f00,0xbf000000,0xbf00,0x3f000000,0xbf00,0x3f000000,
0xbd493f00,0xbeff0000,0xbec63eb5,0xbea2beb5,0x3e15befb,0x3ef53dc8,0x3ee2be8e,0x3e713ed5,0xbe713eed,0xbee2be44,0xbef53e44,0xbe15beed,0x3ea2bed5,0x3ec63e8e,0x3effbdc8,0x3d493efb,
0xbdc83f00,0xbefb0000,0xbefb0000,0x3dc8bf00,0x3e8ebeed,0x3ed53e44,0x3ed53e44,0xbe8e3eed,0xbed53eb5,0xbe8ebeb5,0xbe8ebeb5,0x3ed5beb5,0x3efbbe44,0x3dc83eed,0x3dc83eed,0xbefb3e44,
0xbe153f00,0xbef50000,0xbe71beb5,0x3ee2beb5,0x3ec6bed5,0x3ea23e8e,0xbd493efb,0xbeff3dc8,0xbeff3e44,0xbd49beed,0x3ea2beed,0x3ec63e44,0x3ee23dc8,0xbe713efb,0xbef53e8e,0xbe15bed5,
0xbe443f00,0xbeed0000,0x3e44bf00,0x3eed0000,0x3eedbeb5,0x3e443eb5,0xbeed3eb5,0xbe44beb5,0xbeed0000,0x3e44bf00,0x3eed0000,0xbe443f00,0x3e443eb5,0xbeed3eb5,0xbe44beb5,0x3eedbeb5,
0xbe713f00,0xbee20000,0x3ef5beb5,0x3e153eb5,0x3effbe8e,0x3d493ed5,0xbec6bdc8,0x3ea2befb,0xbea2be44,0x3ec6beed,0xbd493eed,0xbeff3e44,0xbe153efb,0xbef53dc8,0x3ee2bed5,0x3e713e8e,
0xbe8e3f00,0xbed50000,0x3ed50000,0xbe8e3f00,0x3efbbe44,0xbdc83eed,0x3dc8beed,0x3efbbe44,0xbdc8beb5,0x3efbbeb5,0xbefb3eb5,0xbdc8beb5,0xbed53eed,0xbe8ebe44,0x3e8e3e44,0xbed53eed,
0xbea23f00,0xbec60000,0x3d493eb5,0xbeff3eb5,0x3ee2bdc8,0xbe713efb,0x3ef5bed5,0x3e153e8e,0x3e15beed,0x3ef5be44,0xbe71be44,0x3ee2beed,0xbeff3e8e,0x3d49bed5,0xbec63efb,0xbea2bdc8,
0x3eb53f00,0xbeb50000,0x3eb53f00,0xbeb50000,0xbeb50000,0xbeb5bf00,0xbeb50000,0xbeb5bf00,0xbeb5bf00,0x3eb50000,0xbeb5bf00,0x3eb50000,0x3eb50000,0x3eb53f00,0x3eb50000,0x3eb53f00,
0xbeff3f00,0x3d490000,0xbea23eb5,0x3ec6beb5,0xbef53efb,0x3e15bdc8,0xbe713e8e,0x3ee2bed5,0xbee23eed,0x3e71be44,0xbe153e44,0x3ef5beed,0xbec63ed5,0x3ea2be8e,0xbd493dc8,0x3effbefb,
0xbefb3f00,0x3dc80000,0x3dc80000,0x3efbbf00,0xbed53eed,0x3e8ebe44,0x3e8ebe44,0x3ed5beed,0xbe8e3eb5,0x3ed5beb5,0x3ed5beb5,0x3e8ebeb5,0xbdc83e44,0x3efbbeed,0x3efbbeed,0x3dc8be44,
0xbef53f00,0x3e150000,0x3ee2beb5,0x3e71beb5,0xbea23ed5,0x3ec6be8e,0x3effbefb,0xbd49bdc8,0xbd493e44,0x3effbeed,0x3ec6beed,0xbea23e44,0x3e71bdc8,0x3ee2befb,0x3e15be8e,0xbef53ed5,
0xbeed3f00,0x3e440000,0x3eedbf00,0xbe440000,0xbe443eb5,0x3eedbeb5,0x3e44beb5,0xbeed3eb5,0x3e440000,0x3eedbf00,0xbe440000,0xbeed3f00,0x3eedbeb5,0x3e44beb5,0xbeed3eb5,0xbe443eb5,
0xbee23f00,0x3e710000,0x3e15beb5,0xbef53eb5,0xbd493e8e,0x3effbed5,0xbea23dc8,0xbec63efb,0x3ec6be44,0x3ea2beed,0xbeff3eed,0x3d493e44,0x3ef5befb,0xbe15bdc8,0xbe713ed5,0x3ee2be8e,
0xbed53f00,0x3e8e0000,0xbe8e0000,0xbed53f00,0x3dc83e44,0x3efbbeed,0xbefb3eed,0x3dc83e44,0x3efbbeb5,0x3dc8beb5,0xbdc83eb5,0x3efbbeb5,0x3e8ebeed,0xbed53e44,0x3ed5be44,0x3e8ebeed,
0xbec63f00,0x3ea20000,0xbeff3eb5,0xbd493eb5,0x3e713dc8,0x3ee2befb,0xbe153ed5,0x3ef5be8e,0x3ef5beed,0xbe15be44,0x3ee2be44,0x3e71beed,0xbd49be8e,0xbeff3ed5,0x3ea2befb,0xbec63dc8,
0xbeb53f00,0xbeb50000,0xbeb53f00,0xbeb50000,0x3eb50000,0xbeb53f00,0x3eb50000,0xbeb53f00,0x3eb5bf00,0x3eb50000,0x3eb5bf00,0x3eb50000,0xbeb50000,0x3eb5bf00,0xbeb50000,0x3eb5bf00,
0x3d493f00,0x3eff0000,0x3ec63eb5,0x3ea2beb5,0xbe15befb,0xbef53dc8,0xbee2be8e,0xbe713ed5,0x3e713eed,0x3ee2be44,0x3ef53e44,0x3e15beed,0xbea2bed5,0xbec63e8e,0xbeffbdc8,0xbd493efb,
0x3dc83f00,0x3efb0000,0x3efb0000,0xbdc8bf00,0xbe8ebeed,0xbed53e44,0xbed53e44,0x3e8e3eed,0x3ed53eb5,0x3e8ebeb5,0x3e8ebeb5,0xbed5beb5,0xbefbbe44,0xbdc83eed,0xbdc83eed,0x3efb3e44,
0x3e153f00,0x3ef50000,0x3e71beb5,0xbee2beb5,0xbec6bed5,0xbea23e8e,0x3d493efb,0x3eff3dc8,0x3eff3e44,0x3d49beed,0xbea2beed,0xbec63e44,0xbee23dc8,0x3e713efb,0x3ef53e8e,0x3e15bed5,
0x3e443f00,0x3eed0000,0xbe44bf00,0xbeed0000,0xbeedbeb5,0xbe443eb5,0x3eed3eb5,0x3e44beb5,0x3eed0000,0xbe44bf00,0xbeed0000,0x3e443f00,0xbe443eb5,0x3eed3eb5,0x3e44beb5,0xbeedbeb5,
0x3e713f00,0x3ee20000,0xbef5beb5,0xbe153eb5,0xbeffbe8e,0xbd493ed5,0x3ec6bdc8,0xbea2befb,0x3ea2be44,0xbec6beed,0x3d493eed,0x3eff3e44,0x3e153efb,0x3ef53dc8,0xbee2bed5,0xbe713e8e,
0x3e8e3f00,0x3ed50000,0xbed50000,0x3e8e3f00,0xbefbbe44,0x3dc83eed,0xbdc8beed,0xbefbbe44,0x3dc8beb5,0xbefbbeb5,0x3efb3eb5,0x3dc8beb5,0x3ed53eed,0x3e8ebe44,0xbe8e3e44,0x3ed53eed,
0x3ea23f00,0x3ec60000,0xbd493eb5,0x3eff3eb5,0xbee2bdc8,0x3e713efb,0xbef5bed5,0xbe153e8e,0xbe15beed,0xbef5be44,0x3e71be44,0xbee2beed,0x3eff3e8e,0xbd49bed5,0x3ec63efb,0x3ea2bdc8,
0x3f003f00,0xbf003f00,0x3f003f00,0xbf003f00,0x3f003f00,0xbf003f00,0x3f003f00,0xbf003f00,0x3f003f00,0xbf003f00,0x3f003f00,0xbf003f00,0x3f003f00,0xbf003f00,0x3f003f00,0xbf003f00,
0xbd490000,0xbeffbf00,0xbec6beb5,0xbea2beb5,0xbe15bdc8,0xbef5befb,0xbee2bed5,0xbe71be8e,0xbe71be44,0xbee2beed,0xbef5beed,0xbe15be44,0xbea2be8e,0xbec6bed5,0xbeffbefb,0xbd49bdc8,
0xbefbbf00,0x3dc80000,0x3dc80000,0x3efb3f00,0xbed5beed,0x3e8e3e44,0x3e8e3e44,0x3ed53eed,0xbe8ebeb5,0x3ed53eb5,0x3ed53eb5,0x3e8e3eb5,0xbdc8be44,0x3efb3eed,0x3efb3eed,0x3dc83e44,
0x3e150000,0x3ef53f00,0x3e713eb5,0xbee2beb5,0x3ec63e8e,0x3ea23ed5,0xbd493dc8,0xbeffbefb,0x3eff3eed,0x3d493e44,0xbea2be44,0xbec6beed,0x3ee23efb,0xbe71bdc8,0xbef5bed5,0xbe15be8e,
0x3eed3f00,0xbe440000,0xbeedbf00,0x3e440000,0x3e443eb5,0xbeedbeb5,0xbe44beb5,0x3eed3eb5,0xbe440000,0xbeedbf00,0x3e440000,0x3eed3f00,0xbeedbeb5,0xbe44beb5,0x3eed3eb5,0x3e443eb5,
0xbe710000,0xbee2bf00,0x3ef53eb5,0x3e153eb5,0xbeffbed5,0xbd49be8e,0x3ec63efb,0xbea2bdc8,0xbea2beed,0x3ec63e44,0xbd493e44,0xbeffbeed,0x3e15bdc8,0x3ef53efb,0xbee2be8e,0xbe71bed5,
0xbed5bf00,0x3e8e0000,0xbe8e0000,0xbed5bf00,0x3dc8be44,0x3efb3eed,0xbefbbeed,0x3dc8be44,0x3efb3eb5,0x3dc83eb5,0xbdc8beb5,0x3efb3eb5,0x3e8e3eed,0xbed5be44,0x3ed53e44,0x3e8e3eed,
0x3ea20000,0x3ec63f00,0xbd49beb5,0x3eff3eb5,0x3ee23efb,0xbe713dc8,0x3ef53e8e,0x3e153ed5,0xbe153e44,0xbef5beed,0x3e713eed,0xbee2be44,0xbeffbed5,0x3d49be8e,0xbec6bdc8,0xbea2befb,
0x3f00,0xbf000000,0x3f00,0xbf000000,0xbf00,0x3f000000,0xbf00,0x3f000000,0x3f00,0xbf000000,0x3f00,0xbf000000,0xbf00,0x3f000000,0xbf00,0x3f000000,
0xbeff0000,0x3d49bf00,0xbea2beb5,0x3ec6beb5,0x3ef53dc8,0xbe153efb,0x3e713ed5,0xbee23e8e,0xbee2be44,0x3e71beed,0xbe15beed,0x3ef5be44,0x3ec63e8e,0xbea23ed5,0x3d493efb,0xbeff3dc8,
0x3dc8bf00,0x3efb0000,0x3efb0000,0xbdc83f00,0xbe8e3eed,0xbed5be44,0xbed5be44,0x3e8ebeed,0x3ed5beb5,0x3e8e3eb5,0x3e8e3eb5,0xbed53eb5,0xbefb3e44,0xbdc8beed,0xbdc8beed,0x3efbbe44,
0x3ef50000,0xbe153f00,0xbee23eb5,0xbe71beb5,0xbea2be8e,0x3ec6bed5,0x3effbdc8,0xbd493efb,0x3d493eed,0xbeff3e44,0xbec6be44,0x3ea2beed,0x3e71befb,0x3ee23dc8,0x3e153ed5,0xbef53e8e,
0xbe443f00,0xbeed0000,0x3e44bf00,0x3eed0000,0x3eedbeb5,0x3e443eb5,0xbeed3eb5,0xbe44beb5,0xbeed0000,0x3e44bf00,0x3eed0000,0xbe443f00,0x3e443eb5,0xbeed3eb5,0xbe44beb5,0x3eedbeb5,
0xbee20000,0x3e71bf00,0x3e153eb5,0xbef53eb5,0x3d493ed5,0xbeff3e8e,0x3ea2befb,0x3ec63dc8,0x3ec6beed,0x3ea23e44,0xbeff3e44,0x3d49beed,0xbef53dc8,0x3e15befb,0x3e713e8e,0xbee23ed5,
0x3e8ebf00,0x3ed50000,0xbed50000,0x3e8ebf00,0xbefb3e44,0x3dc8beed,0xbdc83eed,0xbefb3e44,0x3dc83eb5,0xbefb3eb5,0x3efbbeb5,0x3dc83eb5,0x3ed5beed,0x3e8e3e44,0xbe8ebe44,0x3ed5beed,
0x3ec60000,0xbea23f00,0x3effbeb5,0x3d493eb5,0x3e71befb,0x3ee2bdc8,0xbe15be8e,0x3ef5bed5,0xbef53e44,0x3e15beed,0xbee23eed,0xbe71be44,0xbd493ed5,0xbeff3e8e,0x3ea23dc8,0xbec63efb,
0x3eb53f00,0xbeb50000,0x3eb53f00,0xbeb50000,0xbeb50000,0xbeb5bf00,0xbeb50000,0xbeb5bf00,0xbeb5bf00,0x3eb50000,0xbeb5bf00,0x3eb50000,0x3eb50000,0x3eb53f00,0x3eb50000,0x3eb53f00,
0x3d490000,0x3effbf00,0x3ec6beb5,0x3ea2beb5,0x3e15bdc8,0x3ef5befb,0x3ee2bed5,0x3e71be8e,0x3e71be44,0x3ee2beed,0x3ef5beed,0x3e15be44,0x3ea2be8e,0x3ec6bed5,0x3effbefb,0x3d49bdc8,
0x3efbbf00,0xbdc80000,0xbdc80000,0xbefb3f00,0x3ed5beed,0xbe8e3e44,0xbe8e3e44,0xbed53eed,0x3e8ebeb5,0xbed53eb5,0xbed53eb5,0xbe8e3eb5,0x3dc8be44,0xbefb3eed,0xbefb3eed,0xbdc83e44,
0xbe150000,0xbef53f00,0xbe713eb5,0x3ee2beb5,0xbec63e8e,0xbea23ed5,0x3d493dc8,0x3effbefb,0xbeff3eed,0xbd493e44,0x3ea2be44,0x3ec6beed,0xbee23efb,0x3e71bdc8,0x3ef5bed5,0x3e15be8e,
0xbeed3f00,0x3e440000,0x3eedbf00,0xbe440000,0xbe443eb5,0x3eedbeb5,0x3e44beb5,0xbeed3eb5,0x3e440000,0x3eedbf00,0xbe440000,0xbeed3f00,0x3eedbeb5,0x3e44beb5,0xbeed3eb5,0xbe443eb5,
0x3e710000,0x3ee2bf00,0xbef53eb5,0xbe153eb5,0x3effbed5,0x3d49be8e,0xbec63efb,0x3ea2bdc8,0x3ea2beed,0xbec63e44,0x3d493e44,0x3effbeed,0xbe15bdc8,0xbef53efb,0x3ee2be8e,0x3e71bed5,
0x3ed5bf00,0xbe8e0000,0x3e8e0000,0x3ed5bf00,0xbdc8be44,0xbefb3eed,0x3efbbeed,0xbdc8be44,0xbefb3eb5,0xbdc83eb5,0x3dc8beb5,0xbefb3eb5,0xbe8e3eed,0x3ed5be44,0xbed53e44,0xbe8e3eed,
0xbea20000,0xbec63f00,0x3d49beb5,0xbeff3eb5,0xbee23efb,0x3e713dc8,0xbef53e8e,0xbe153ed5,0x3e153e44,0x3ef5beed,0xbe713eed,0x3ee2be44,0x3effbed5,0xbd49be8e,0x3ec6bdc8,0x3ea2befb,
0xbeb53f00,0xbeb50000,0xbeb53f00,0xbeb50000,0x3eb50000,0xbeb53f00,0x3eb50000,0xbeb53f00,0x3eb5bf00,0x3eb50000,0x3eb5bf00,0x3eb50000,0xbeb50000,0x3eb5bf00,0xbeb50000,0x3eb5bf00,
0x3eff0000,0xbd49bf00,0x3ea2beb5,0xbec6beb5,0xbef53dc8,0x3e153efb,0xbe713ed5,0x3ee23e8e,0x3ee2be44,0xbe71beed,0x3e15beed,0xbef5be44,0xbec63e8e,0x3ea23ed5,0xbd493efb,0x3eff3dc8,
0xbdc8bf00,0xbefb0000,0xbefb0000,0x3dc83f00,0x3e8e3eed,0x3ed5be44,0x3ed5be44,0xbe8ebeed,0xbed5beb5,0xbe8e3eb5,0xbe8e3eb5,0x3ed53eb5,0x3efb3e44,0x3dc8beed,0x3dc8beed,0xbefbbe44,
0xbef50000,0x3e153f00,0x3ee23eb5,0x3e71beb5,0x3ea2be8e,0xbec6bed5,0xbeffbdc8,0x3d493efb,0xbd493eed,0x3eff3e44,0x3ec6be44,0xbea2beed,0xbe71befb,0xbee23dc8,0xbe153ed5,0x3ef53e8e,
0x3e443f00,0x3eed0000,0xbe44bf00,0xbeed0000,0xbeedbeb5,0xbe443eb5,0x3eed3eb5,0x3e44beb5,0x3eed0000,0xbe44bf00,0xbeed0000,0x3e443f00,0xbe443eb5,0x3eed3eb5,0x3e44beb5,0xbeedbeb5,
0x3ee20000,0xbe71bf00,0xbe153eb5,0x3ef53eb5,0xbd493ed5,0x3eff3e8e,0xbea2befb,0xbec63dc8,0xbec6beed,0xbea23e44,0x3eff3e44,0xbd49beed,0x3ef53dc8,0xbe15befb,0xbe713e8e,0x3ee23ed5,
0xbe8ebf00,0xbed50000,0x3ed50000,0xbe8ebf00,0x3efb3e44,0xbdc8beed,0x3dc83eed,0x3efb3e44,0xbdc83eb5,0x3efb3eb5,0xbefbbeb5,0xbdc83eb5,0xbed5beed,0xbe8e3e44,0x3e8ebe44,0xbed5beed,
0xbec60000,0x3ea23f00,0xbeffbeb5,0xbd493eb5,0xbe71befb,0xbee2bdc8,0x3e15be8e,0xbef5bed5,0x3ef53e44,0xbe15beed,0x3ee23eed,0x3e71be44,0x3d493ed5,0x3eff3e8e,0xbea23dc8,0x3ec63efb,
0x3f003f00,0xbf003f00,0x3f003f00,0xbf003f00,0x3f003f00,0xbf003f00,0x3f003f00,0xbf003f00,0x3f003f00,0xbf003f00,0x3f003f00,0xbf003f00,0x3f003f00,0xbf003f00,0x3f003f00,0xbf003f00,
0xbeffbf00,0x3d490000,0xbea2beb5,0x3ec63eb5,0xbef5befb,0x3e153dc8,0xbe71be8e,0x3ee23ed5,0xbee2beed,0x3e713e44,0xbe15be44,0x3ef53eed,0xbec6bed5,0x3ea23e8e,0xbd49bdc8,0x3eff3efb,
0x3efb3f00,0xbdc80000,0xbdc80000,0xbefbbf00,0x3ed53eed,0xbe8ebe44,0xbe8ebe44,0xbed5beed,0x3e8e3eb5,0xbed5beb5,0xbed5beb5,0xbe8ebeb5,0x3dc83e44,0xbefbbeed,0xbefbbeed,0xbdc8be44,
0xbef5bf00,0x3e150000,0x3ee23eb5,0x3e713eb5,0xbea2bed5,0x3ec63e8e,0x3eff3efb,0xbd493dc8,0xbd49be44,0x3eff3eed,0x3ec63eed,0xbea2be44,0x3e713dc8,0x3ee23efb,0x3e153e8e,0xbef5bed5,
0x3eed3f00,0xbe440000,0xbeedbf00,0x3e440000,0x3e443eb5,0xbeedbeb5,0xbe44beb5,0x3eed3eb5,0xbe440000,0xbeedbf00,0x3e440000,0x3eed3f00,0xbeedbeb5,0xbe44beb5,0x3eed3eb5,0x3e443eb5,
0xbee2bf00,0x3e710000,0x3e153eb5,0xbef5beb5,0xbd49be8e,0x3eff3ed5,0xbea2bdc8,0xbec6befb,0x3ec63e44,0x3ea23eed,0xbeffbeed,0x3d49be44,0x3ef53efb,0xbe153dc8,0xbe71bed5,0x3ee23e8e,
0x3ed53f00,0xbe8e0000,0x3e8e0000,0x3ed53f00,0xbdc83e44,0xbefbbeed,0x3efb3eed,0xbdc83e44,0xbefbbeb5,0xbdc8beb5,0x3dc83eb5,0xbefbbeb5,0xbe8ebeed,0x3ed53e44,0xbed5be44,0xbe8ebeed,
0xbec6bf00,0x3ea20000,0xbeffbeb5,0xbd49beb5,0x3e71bdc8,0x3ee23efb,0xbe15bed5,0x3ef53e8e,0x3ef53eed,0xbe153e44,0x3ee23e44,0x3e713eed,0xbd493e8e,0xbeffbed5,0x3ea23efb,0xbec6bdc8,
0x3f00,0xbf000000,0x3f00,0xbf000000,0xbf00,0x3f000000,0xbf00,0x3f000000,0x3f00,0xbf000000,0x3f00,0xbf000000,0xbf00,0x3f000000,0xbf00,0x3f000000,
0x3d49bf00,0x3eff0000,0x3ec6beb5,0x3ea23eb5,0xbe153efb,0xbef5bdc8,0xbee23e8e,0xbe71bed5,0x3e71beed,0x3ee23e44,0x3ef5be44,0x3e153eed,0xbea23ed5,0xbec6be8e,0xbeff3dc8,0xbd49befb,
0xbdc83f00,0xbefb0000,0xbefb0000,0x3dc8bf00,0x3e8ebeed,0x3ed53e44,0x3ed53e44,0xbe8e3eed,0xbed53eb5,0xbe8ebeb5,0xbe8ebeb5,0x3ed5beb5,0x3efbbe44,0x3dc83eed,0x3dc83eed,0xbefb3e44,
0x3e15bf00,0x3ef50000,0x3e713eb5,0xbee23eb5,0xbec63ed5,0xbea2be8e,0x3d49befb,0x3effbdc8,0x3effbe44,0x3d493eed,0xbea23eed,0xbec6be44,0xbee2bdc8,0x3e71befb,0x3ef5be8e,0x3e153ed5,
0xbe443f00,0xbeed0000,0x3e44bf00,0x3eed0000,0x3eedbeb5,0x3e443eb5,0xbeed3eb5,0xbe44beb5,0xbeed0000,0x3e44bf00,0x3eed0000,0xbe443f00,0x3e443eb5,0xbeed3eb5,0xbe44beb5,0x3eedbeb5,
0x3e71bf00,0x3ee20000,0xbef53eb5,0xbe15beb5,0xbeff3e8e,0xbd49bed5,0x3ec63dc8,0xbea23efb,0x3ea23e44,0xbec63eed,0x3d49beed,0x3effbe44,0x3e15befb,0x3ef5bdc8,0xbee23ed5,0xbe71be8e,
0xbe8e3f00,0xbed50000,0x3ed50000,0xbe8e3f00,0x3efbbe44,0xbdc83eed,0x3dc8beed,0x3efbbe44,0xbdc8beb5,0x3efbbeb5,0xbefb3eb5,0xbdc8beb5,0xbed53eed,0xbe8ebe44,0x3e8e3e44,0xbed53eed,
0x3ea2bf00,0x3ec60000,0xbd49beb5,0x3effbeb5,0xbee23dc8,0x3e71befb,0xbef53ed5,0xbe15be8e,0xbe153eed,0xbef53e44,0x3e713e44,0xbee23eed,0x3effbe8e,0xbd493ed5,0x3ec6befb,0x3ea23dc8,
0x3eb53f00,0xbeb50000,0x3eb53f00,0xbeb50000,0xbeb50000,0xbeb5bf00,0xbeb50000,0xbeb5bf00,0xbeb5bf00,0x3eb50000,0xbeb5bf00,0x3eb50000,0x3eb50000,0x3eb53f00,0x3eb50000,0x3eb53f00,
0x3effbf00,0xbd490000,0x3ea2beb5,0xbec63eb5,0x3ef5befb,0xbe153dc8,0x3e71be8e,0xbee23ed5,0x3ee2beed,0xbe713e44,0x3e15be44,0xbef53eed,0x3ec6bed5,0xbea23e8e,0x3d49bdc8,0xbeff3efb,
0xbefb3f00,0x3dc80000,0x3dc80000,0x3efbbf00,0xbed53eed,0x3e8ebe44,0x3e8ebe44,0x3ed5beed,0xbe8e3eb5,0x3ed5beb5,0x3ed5beb5,0x3e8ebeb5,0xbdc83e44,0x3efbbeed,0x3efbbeed,0x3dc8be44,
0x3ef5bf00,0xbe150000,0xbee23eb5,0xbe713eb5,0x3ea2bed5,0xbec63e8e,0xbeff3efb,0x3d493dc8,0x3d49be44,0xbeff3eed,0xbec63eed,0x3ea2be44,0xbe713dc8,0xbee23efb,0xbe153e8e,0x3ef5bed5,
0xbeed3f00,0x3e440000,0x3eedbf00,0xbe440000,0xbe443eb5,0x3eedbeb5,0x3e44beb5,0xbeed3eb5,0x3e440000,0x3eedbf00,0xbe440000,0xbeed3f00,0x3eedbeb5,0x3e44beb5,0xbeed3eb5,0xbe443eb5,
0x3ee2bf00,0xbe710000,0xbe153eb5,0x3ef5beb5,0x3d49be8e,0xbeff3ed5,0x3ea2bdc8,0x3ec6befb,0xbec63e44,0xbea23eed,0x3effbeed,0xbd49be44,0xbef53efb,0x3e153dc8,0x3e71bed5,0xbee23e8e,
0xbed53f00,0x3e8e0000,0xbe8e0000,0xbed53f00,0x3dc83e44,0x3efbbeed,0xbefb3eed,0x3dc83e44,0x3efbbeb5,0x3dc8beb5,0xbdc83eb5,0x3efbbeb5,0x3e8ebeed,0xbed53e44,0x3ed5be44,0x3e8ebeed,
0x3ec6bf00,0xbea20000,0x3effbeb5,0x3d49beb5,0xbe71bdc8,0xbee23efb,0x3e15bed5,0xbef53e8e,0xbef53eed,0x3e153e44,0xbee23e44,0xbe713eed,0x3d493e8e,0x3effbed5,0xbea23efb,0x3ec6bdc8,
0xbeb53f00,0xbeb50000,0xbeb53f00,0xbeb50000,0x3eb50000,0xbeb53f00,0x3eb50000,0xbeb53f00,0x3eb5bf00,0x3eb50000,0x3eb5bf00,0x3eb50000,0xbeb50000,0x3eb5bf00,0xbeb50000,0x3eb5bf00,
0xbd49bf00,0xbeff0000,0xbec6beb5,0xbea23eb5,0x3e153efb,0x3ef5bdc8,0x3ee23e8e,0x3e71bed5,0xbe71beed,0xbee23e44,0xbef5be44,0xbe153eed,0x3ea23ed5,0x3ec6be8e,0x3eff3dc8,0x3d49befb,
0x3dc83f00,0x3efb0000,0x3efb0000,0xbdc8bf00,0xbe8ebeed,0xbed53e44,0xbed53e44,0x3e8e3eed,0x3ed53eb5,0x3e8ebeb5,0x3e8ebeb5,0xbed5beb5,0xbefbbe44,0xbdc83eed,0xbdc83eed,0x3efb3e44,
0xbe15bf00,0xbef50000,0xbe713eb5,0x3ee23eb5,0x3ec63ed5,0x3ea2be8e,0xbd49befb,0xbeffbdc8,0xbeffbe44,0xbd493eed,0x3ea23eed,0x3ec6be44,0x3ee2bdc8,0xbe71befb,0xbef5be8e,0xbe153ed5,
0x3e443f00,0x3eed0000,0xbe44bf00,0xbeed0000,0xbeedbeb5,0xbe443eb5,0x3eed3eb5,0x3e44beb5,0x3eed0000,0xbe44bf00,0xbeed0000,0x3e443f00,0xbe443eb5,0x3eed3eb5,0x3e44beb5,0xbeedbeb5,
0xbe71bf00,0xbee20000,0x3ef53eb5,0x3e15beb5,0x3eff3e8e,0x3d49bed5,0xbec63dc8,0x3ea23efb,0xbea23e44,0x3ec63eed,0xbd49beed,0xbeffbe44,0xbe15befb,0xbef5bdc8,0x3ee23ed5,0x3e71be8e,
0x3e8e3f00,0x3ed50000,0xbed50000,0x3e8e3f00,0xbefbbe44,0x3dc83eed,0xbdc8beed,0xbefbbe44,0x3dc8beb5,0xbefbbeb5,0x3efb3eb5,0x3dc8beb5,0x3ed53eed,0x3e8ebe44,0xbe8e3e44,0x3ed53eed,
0xbea2bf00,0xbec60000,0x3d49beb5,0xbeffbeb5,0x3ee23dc8,0xbe71befb,0x3ef53ed5,0x3e15be8e,0x3e153eed,0x3ef53e44,0xbe713e44,0x3ee23eed,0xbeffbe8e,0x3d493ed5,0xbec6befb,0xbea23dc8,
0x3f003f00,0xbf003f00,0x3f003f00,0xbf003f00,0x3f003f00,0xbf003f00,0x3f003f00,0xbf003f00,0x3f003f00,0xbf003f00,0x3f003f00,0xbf003f00,0x3f003f00,0xbf003f00,0x3f003f00,0xbf003f00,
0x3d490000,0x3eff3f00,0x3ec63eb5,0x3ea23eb5,0x3e153dc8,0x3ef53efb,0x3ee23ed5,0x3e713e8e,0x3e713e44,0x3ee23eed,0x3ef53eed,0x3e153e44,0x3ea23e8e,0x3ec63ed5,0x3eff3efb,0x3d493dc8,
0xbefbbf00,0x3dc80000,0x3dc80000,0x3efb3f00,0xbed5beed,0x3e8e3e44,0x3e8e3e44,0x3ed53eed,0xbe8ebeb5,0x3ed53eb5,0x3ed53eb5,0x3e8e3eb5,0xbdc8be44,0x3efb3eed,0x3efb3eed,0x3dc83e44,
0xbe150000,0xbef5bf00,0xbe71beb5,0x3ee23eb5,0xbec6be8e,0xbea2bed5,0x3d49bdc8,0x3eff3efb,0xbeffbeed,0xbd49be44,0x3ea23e44,0x3ec63eed,0xbee2befb,0x3e713dc8,0x3ef53ed5,0x3e153e8e,
0x3eed3f00,0xbe440000,0xbeedbf00,0x3e440000,0x3e443eb5,0xbeedbeb5,0xbe44beb5,0x3eed3eb5,0xbe440000,0xbeedbf00,0x3e440000,0x3eed3f00,0xbeedbeb5,0xbe44beb5,0x3eed3eb5,0x3e443eb5,
0x3e710000,0x3ee23f00,0xbef5beb5,0xbe15beb5,0x3eff3ed5,0x3d493e8e,0xbec6befb,0x3ea23dc8,0x3ea23eed,0xbec6be44,0x3d49be44,0x3eff3eed,0xbe153dc8,0xbef5befb,0x3ee23e8e,0x3e713ed5,
0xbed5bf00,0x3e8e0000,0xbe8e0000,0xbed5bf00,0x3dc8be44,0x3efb3eed,0xbefbbeed,0x3dc8be44,0x3efb3eb5,0x3dc83eb5,0xbdc8beb5,0x3efb3eb5,0x3e8e3eed,0xbed5be44,0x3ed53e44,0x3e8e3eed,
0xbea20000,0xbec6bf00,0x3d493eb5,0xbeffbeb5,0xbee2befb,0x3e71bdc8,0xbef5be8e,0xbe15bed5,0x3e15be44,0x3ef53eed,0xbe71beed,0x3ee23e44,0x3eff3ed5,0xbd493e8e,0x3ec63dc8,0x3ea23efb,
0x3f00,0xbf000000,0x3f00,0xbf000000,0xbf00,0x3f000000,0xbf00,0x3f000000,0x3f00,0xbf000000,0x3f00,0xbf000000,0xbf00,0x3f000000,0xbf00,0x3f000000,
0x3eff0000,0xbd493f00,0x3ea23eb5,0xbec63eb5,0xbef5bdc8,0x3e15befb,0xbe71bed5,0x3ee2be8e,0x3ee23e44,0xbe713eed,0x3e153eed,0xbef53e44,0xbec6be8e,0x3ea2bed5,0xbd49befb,0x3effbdc8,
0x3dc8bf00,0x3efb0000,0x3efb0000,0xbdc83f00,0xbe8e3eed,0xbed5be44,0xbed5be44,0x3e8ebeed,0x3ed5beb5,0x3e8e3eb5,0x3e8e3eb5,0xbed53eb5,0xbefb3e44,0xbdc8beed,0xbdc8beed,0x3efbbe44,
0xbef50000,0x3e15bf00,0x3ee2beb5,0x3e713eb5,0x3ea23e8e,0xbec63ed5,0xbeff3dc8,0x3d49befb,0xbd49beed,0x3effbe44,0x3ec63e44,0xbea23eed,0xbe713efb,0xbee2bdc8,0xbe15bed5,0x3ef5be8e,
0xbe443f00,0xbeed0000,0x3e44bf00,0x3eed0000,0x3eedbeb5,0x3e443eb5,0xbeed3eb5,0xbe44beb5,0xbeed0000,0x3e44bf00,0x3eed0000,0xbe443f00,0x3e443eb5,0xbeed3eb5,0xbe44beb5,0x3eedbeb5,
0x3ee20000,0xbe713f00,0xbe15beb5,0x3ef5beb5,0xbd49bed5,0x3effbe8e,0xbea23efb,0xbec6bdc8,0xbec63eed,0xbea2be44,0x3effbe44,0xbd493eed,0x3ef5bdc8,0xbe153efb,0xbe71be8e,0x3ee2bed5,
0x3e8ebf00,0x3ed50000,0xbed50000,0x3e8ebf00,0xbefb3e44,0x3dc8beed,0xbdc83eed,0xbefb3e44,0x3dc83eb5,0xbefb3eb5,0x3efbbeb5,0x3dc83eb5,0x3ed5beed,0x3e8e3e44,0xbe8ebe44,0x3ed5beed,
0xbec60000,0x3ea2bf00,0xbeff3eb5,0xbd49beb5,0xbe713efb,0xbee23dc8,0x3e153e8e,0xbef53ed5,0x3ef5be44,0xbe153eed,0x3ee2beed,0x3e713e44,0x3d49bed5,0x3effbe8e,0xbea2bdc8,0x3ec6befb,
0x3eb53f00,0xbeb50000,0x3eb53f00,0xbeb50000,0xbeb50000,0xbeb5bf00,0xbeb50000,0xbeb5bf00,0xbeb5bf00,0x3eb50000,0xbeb5bf00,0x3eb50000,0x3eb50000,0x3eb53f00,0x3eb50000,0x3eb53f00,
0xbd490000,0xbeff3f00,0xbec63eb5,0xbea23eb5,0xbe153dc8,0xbef53efb,0xbee23ed5,0xbe713e8e,0xbe713e44,0xbee23eed,0xbef53eed,0xbe153e44,0xbea23e8e,0xbec63ed5,0xbeff3efb,0xbd493dc8,
0x3efbbf00,0xbdc80000,0xbdc80000,0xbefb3f00,0x3ed5beed,0xbe8e3e44,0xbe8e3e44,0xbed53eed,0x3e8ebeb5,0xbed53eb5,0xbed53eb5,0xbe8e3eb5,0x3dc8be44,0xbefb3eed,0xbefb3eed,0xbdc83e44,
0x3e150000,0x3ef5bf00,0x3e71beb5,0xbee23eb5,0x3ec6be8e,0x3ea2bed5,0xbd49bdc8,0xbeff3efb,0x3effbeed,0x3d49be44,0xbea23e44,0xbec63eed,0x3ee2befb,0xbe713dc8,0xbef53ed5,0xbe153e8e,
0xbeed3f00,0x3e440000,0x3eedbf00,0xbe440000,0xbe443eb5,0x3eedbeb5,0x3e44beb5,0xbeed3eb5,0x3e440000,0x3eedbf00,0xbe440000,0xbeed3f00,0x3eedbeb5,0x3e44beb5,0xbeed3eb5,0xbe443eb5,
0xbe710000,0xbee23f00,0x3ef5beb5,0x3e15beb5,0xbeff3ed5,0xbd493e8e,0x3ec6befb,0xbea23dc8,0xbea23eed,0x3ec6be44,0xbd49be44,0xbeff3eed,0x3e153dc8,0x3ef5befb,0xbee23e8e,0xbe713ed5,
0x3ed5bf00,0xbe8e0000,0x3e8e0000,0x3ed5bf00,0xbdc8be44,0xbefb3eed,0x3efbbeed,0xbdc8be44,0xbefb3eb5,0xbdc83eb5,0x3dc8beb5,0xbefb3eb5,0xbe8e3eed,0x3ed5be44,0xbed53e44,0xbe8e3eed,
0x3ea20000,0x3ec6bf00,0xbd493eb5,0x3effbeb5,0x3ee2befb,0xbe71bdc8,0x3ef5be8e,0x3e15bed5,0xbe15be44,0xbef53eed,0x3e71beed,0xbee23e44,0xbeff3ed5,0x3d493e8e,0xbec63dc8,0xbea23efb,
0xbeb53f00,0xbeb50000,0xbeb53f00,0xbeb50000,0x3eb50000,0xbeb53f00,0x3eb50000,0xbeb53f00,0x3eb5bf00,0x3eb50000,0x3eb5bf00,0x3eb50000,0xbeb50000,0x3eb5bf00,0xbeb50000,0x3eb5bf00,
0xbeff0000,0x3d493f00,0xbea23eb5,0x3ec63eb5,0x3ef5bdc8,0xbe15befb,0x3e71bed5,0xbee2be8e,0xbee23e44,0x3e713eed,0xbe153eed,0x3ef53e44,0x3ec6be8e,0xbea2bed5,0x3d49befb,0xbeffbdc8,
0xbdc8bf00,0xbefb0000,0xbefb0000,0x3dc83f00,0x3e8e3eed,0x3ed5be44,0x3ed5be44,0xbe8ebeed,0xbed5beb5,0xbe8e3eb5,0xbe8e3eb5,0x3ed53eb5,0x3efb3e44,0x3dc8beed,0x3dc8beed,0xbefbbe44,
0x3ef50000,0xbe15bf00,0xbee2beb5,0xbe713eb5,0xbea23e8e,0x3ec63ed5,0x3eff3dc8,0xbd49befb,0x3d49beed,0xbeffbe44,0xbec63e44,0x3ea23eed,0x3e713efb,0x3ee2bdc8,0x3e15bed5,0xbef5be8e,
0x3e443f00,0x3eed0000,0xbe44bf00,0xbeed0000,0xbeedbeb5,0xbe443eb5,0x3eed3eb5,0x3e44beb5,0x3eed0000,0xbe44bf00,0xbeed0000,0x3e443f00,0xbe443eb5,0x3eed3eb5,0x3e44beb5,0xbeedbeb5,
0xbee20000,0x3e713f00,0x3e15beb5,0xbef5beb5,0x3d49bed5,0xbeffbe8e,0x3ea23efb,0x3ec6bdc8,0x3ec63eed,0x3ea2be44,0xbeffbe44,0x3d493eed,0xbef5bdc8,0x3e153efb,0x3e71be8e,0xbee2bed5,
0xbe8ebf00,0xbed50000,0x3ed50000,0xbe8ebf00,0x3efb3e44,0xbdc8beed,0x3dc83eed,0x3efb3e44,0xbdc83eb5,0x3efb3eb5,0xbefbbeb5,0xbdc83eb5,0xbed5beed,0xbe8e3e44,0x3e8ebe44,0xbed5beed,
0x3ec60000,0xbea2bf00,0x3eff3eb5,0x3d49beb5,0x3e713efb,0x3ee23dc8,0xbe153e8e,0x3ef53ed5,0xbef5be44,0x3e153eed,0xbee2beed,0xbe713e44,0xbd49bed5,0xbeffbe8e,0x3ea2bdc8,0xbec6befb,
0x3f800000,0x0,0x3f800000,0x0,0x3f800000,0x0,0x3f800000,0x0,0x3f800000,0x0,0x3f800000,0x0,0x3f800000,0x0,0x3f800000,0x0,
0x3f800000,0x0,0x3f7fec43,0xbcc90ab0,0x3f7fb10f,0xbd48fb30,0x3f7f4e6d,0xbd96a905,0x3f7ec46d,0xbdc8bd36,0x3f7e1324,0xbdfab273,0x3f7d3aac,0xbe164083,0x3f7c3b28,0xbe2f10a2,
0x3f800000,0x0,0x3f7ffec4,0xbbc90f88,0x3f7ffb11,0xbc490e90,0x3f7ff4e6,0xbc96c9b6,0x3f7fec43,0xbcc90ab0,0x3f7fe129,0xbcfb49ba,0x3f7fd397,0xbd16c32c,0x3f7fc38f,0xbd2fe007,
0x3f800000,0x0,0x3f7fe129,0xbcfb49ba,0x3f7f84ab,0xbd7b2b74,0x3f7eea9d,0xbdbc3ac3,0x3f7e1324,0xbdfab273,0x3f7cfe73,0xbe1c76de,0x3f7baccd,0xbe3b6ecf,0x3f7a1e84,0xbe5a3997,
0x3f800000,0x0,0x3f7ffb11,0xbc490e90,0x3f7fec43,0xbcc90ab0,0x3f7fd397,0xbd16c32c,0x3f7fb10f,0xbd48fb30,0x3f7f84ab,0xbd7b2b74,0x3f7f4e6d,0xbd96a905,0x3f7f0e58,0xbdafb680,
0x3f800000,0x0,0x3f7fd397,0xbd16c32c,0x3f7f4e6d,0xbd96a905,0x3f7e70b0,0xbde1bc2e,0x3f7d3aac,0xbe164083,0x3f7baccd,0xbe3b6ecf,0x3f79c79d,0xbe605c13,0x3f778bc5,0xbe827dc0,
0x3f800000,0x0,0x3f7ff4e6,0xbc96c9b6,0x3f7fd397,0xbd16c32c,0x3f7f9c18,0xbd621469,0x3f7f4e6d,0xbd96a905,0x3f7eea9d,0xbdbc3ac3,0x3f7e70b0,0xbde1bc2e,0x3f7de0b1,0xbe039502,
0x3f800000,0x0,0x3f7fc38f,0xbd2fe007,0x3f7f0e58,0xbdafb680,0x3f7de0b1,0xbe039502,0x3f7c3b28,0xbe2f10a2,0x3f7a1e84,0xbe5a3997,0x3f778bc5,0xbe827dc0,0x3f748422,0xbe97a117,
0x3f800000,0x0,0x3f7fb10f,0xbd48fb30,0x3f7ec46d,0xbdc8bd36,0x3f7d3aac,0xbe164083,0x3f7b14be,0xbe47c5c2,0x3f7853f8,0xbe78cfcc,0x3f74fa0b,0xbe94a031,0x3f710908,0xbeac7cd4,
0x3f800000,0x0,0x3f7f4e6d,0xbd96a905,0x3f7d3aac,0xbe164083,0x3f79c79d,0xbe605c13,0x3f74fa0b,0xbe94a031,0x3f6ed89e,0xbeb8442a,0x3f676bd8,0xbedae880,0x3f5ebe05,0xbefc5d27,
0x3f800000,0x0,0x3f7f9c18,0xbd621469,0x3f7e70b0,0xbde1bc2e,0x3f7c7eb0,0xbe28defc,0x3f79c79d,0xbe605c13,0x3f764d97,0xbe8b9507,0x3f721352,0xbea68f12,0x3f6d1c1d,0xbec1071e,
0x3f800000,0x0,0x3f7f2f9d,0xbda3308c,0x3f7cbfc9,0xbe22abb6,0x3f78b47b,0xbe72b651,0x3f731447,0xbea09ae5,0x3f6be858,0xbec6d529,0x3f633c5a,0xbeebcbbb,0x3f591e6a,0xbf07a136,
0x3f800000,0x0,0x3f7f84ab,0xbd7b2b74,0x3f7e1324,0xbdfab273,0x3f7baccd,0xbe3b6ecf,0x3f7853f8,0xbe78cfcc,0x3f740bdd,0xbe9aa086,0x3f6ed89e,0xbeb8442a,0x3f68bf3c,0xbed53641,
0x3f800000,0x0,0x3f7f0e58,0xbdafb680,0x3f7c3b28,0xbe2f10a2,0x3f778bc5,0xbe827dc0,0x3f710908,0xbeac7cd4,0x3f68bf3c,0xbed53641,0x3f5ebe05,0xbefc5d27,0x3f531849,0xbf10d3cd,
0x3f800000,0x0,0x3f7f6ac7,0xbd8a200a,0x3f7dabcc,0xbe09cf86,0x3f7ac516,0xbe4dee60,0x3f76ba07,0xbe888e93,0x3f718f57,0xbea986c4,0x3f6b4b0c,0xbec9b953,0x3f63f473,0xbee900b7,
0x3f800000,0x0,0x3f7eea9d,0xbdbc3ac3,0x3f7baccd,0xbe3b6ecf,0x3f764d97,0xbe8b9507,0x3f6ed89e,0xbeb8442a,0x3f655e0b,0xbee363fa,0x3f59f26a,0xbf064b82,0x3f4cae79,0xbf19c200,
0x3f800000,0x0,0x3f7ec46d,0xbdc8bd36,0x3f7b14be,0xbe47c5c2,0x3f74fa0b,0xbe94a031,0x3f6c835e,0xbec3ef15,0x3f61c598,0xbef15aea,0x3f54db31,0xbf0e39da,0x3f45e403,0xbf226799,
0x3f800000,0x0,0x3f7e1324,0xbdfab273,0x3f7853f8,0xbe78cfcc,0x3f6ed89e,0xbeb8442a,0x3f61c598,0xbef15aea,0x3f514d3d,0xbf13682a,0x3f3daef9,0xbf2beb4a,0x3f273656,0xbf41d870,
0x3f800000,0x0,0x3f7e9bc9,0xbdd53db9,0x3f7a7302,0xbe541501,0x3f73913f,0xbe9d9e78,0x3f6a09a7,0xbecf7bca,0x3f5df6be,0xbeff17b2,0x3f4f7a1f,0xbf15f6d9,0x3f3ebc1b,0xbf2ac082,
0x3f800000,0x0,0x3f7de0b1,0xbe039502,0x3f778bc5,0xbe827dc0,0x3f6d1c1d,0xbec1071e,0x3f5ebe05,0xbefc5d27,0x3f4cae79,0xbf19c200,0x3f373a23,0xbf32c8c9,0x3f1ebc12,0xbf48d8b3,
0x3f800000,0x0,0x3f7e70b0,0xbde1bc2e,0x3f79c79d,0xbe605c13,0x3f721352,0xbea68f12,0x3f676bd8,0xbedae880,0x3f59f26a,0xbf064b82,0x3f49d112,0xbf1d7fd1,0x3f373a23,0xbf32c8c9,
0x3f800000,0x0,0x3f7dabcc,0xbe09cf86,0x3f76ba07,0xbe888e93,0x3f6b4b0c,0xbec9b953,0x3f5b941a,0xbf039c3d,0x3f47de65,0xbf1ff6cb,0x3f3085bb,0xbf396842,0x3f15f6d9,0xbf4f7a1f,
0x3f800000,0x0,0x3f7e4323,0xbdee3876,0x3f791298,0xbe6c9a7f,0x3f708066,0xbeaf713a,0x3f64aa59,0xbee63375,0x3f55b993,0xbf0cead0,0x3f43e200,0xbf24d225,0x3f2f61a5,0xbf3a7ca4,
0x3f800000,0x0,0x3f7d7474,0xbe1008b7,0x3f75dec6,0xbe8e9a22,0x3f696591,0xbed25a09,0x3f584853,0xbf08f59b,0x3f42de29,0xbf26050a,0x3f299415,0xbf3fc767,0x3f0cead0,0xbf55b993,
0x3f800000,0x0,0x3f7d3aac,0xbe164083,0x3f74fa0b,0xbe94a031,0x3f676bd8,0xbedae880,0x3f54db31,0xbf0e39da,0x3f3daef9,0xbf2beb4a,0x3f226799,0xbf45e403,0x3f039c3d,0xbf5b941a,
0x3f800000,0x0,0x3f7c3b28,0xbe2f10a2,0x3f710908,0xbeac7cd4,0x3f5ebe05,0xbefc5d27,0x3f45e403,0xbf226799,0x3f273656,0xbf41d870,0x3f039c3d,0xbf5b941a,0x3eb8442a,0xbf6ed89e,
0x3f800000,0x0,0x3f7cfe73,0xbe1c76de,0x3f740bdd,0xbe9aa086,0x3f655e0b,0xbee363fa,0x3f514d3d,0xbf13682a,0x3f385216,0xbf31a81d,0x3f1b02c6,0xbf4bbbf8,0x3ef41f07,0xbf6106f2,
0x3f800000,0x0,0x3f7bf531,0xbe354098,0x3f6ff573,0xbeb263ef,0x3f5c61c7,0xbf0242b1,0x3f41d870,0xbf273656,0x3f212ff9,0xbf46e22a,0x3ef6e0cb,0xbf604621,0x3ea395c5,0xbf7294f8,
0x3f800000,0x0,0x3f7cbfc9,0xbe22abb6,0x3f731447,0xbea09ae5,0x3f633c5a,0xbeebcbbb,0x3f4d9f02,0xbf187fc0,0x3f32c8c9,0xbf373a23,0x3f13682a,0xbf514d3d,0x3ee0924f,0xbf660f88,
0x3f800000,0x0,0x3f7baccd,0xbe3b6ecf,0x3f6ed89e,0xbeb8442a,0x3f59f26a,0xbf064b82,0x3f3daef9,0xbf2beb4a,0x3f1b02c6,0xbf4bbbf8,0x3ee63375,0xbf64aa59,0x3e8e9a22,0xbf75dec6,
0x3f800000,0x0,0x3f7c7eb0,0xbe28defc,0x3f721352,0xbea68f12,0x3f6106f2,0xbef41f07,0x3f49d112,0xbf1d7fd1,0x3f2d1469,0xbf3ca003,0x3f0b9a6b,0xbf5695e5,0x3ecc9b8b,0xbf6aab7b,
0x3f800000,0x0,0x3f7b61fc,0xbe419b37,0x3f6db293,0xbebe1d4a,0x3f577026,0xbf0a48ad,0x3f396842,0xbf3085bb,0x3f14b039,0xbf5064af,0x3ed53641,0xbf68bf3c,0x3e72b651,0xbf78b47b,
0x3f800000,0x0,0x3f800000,0x0,0x3f800000,0x0,0x3f800000,0x0,0x3f800000,0x0,0x3f800000,0x0,0x3f800000,0x0,0x3f800000,0x0,
0x3f7b14be,0xbe47c5c2,0x3f79c79d,0xbe605c13,0x3f7853f8,0xbe78cfcc,0x3f76ba07,0xbe888e93,0x3f74fa0b,0xbe94a031,0x3f731447,0xbea09ae5,0x3f710908,0xbeac7cd4,0x3f6ed89e,0xbeb8442a,
0x3f7fb10f,0xbd48fb30,0x3f7f9c18,0xbd621469,0x3f7f84ab,0xbd7b2b74,0x3f7f6ac7,0xbd8a200a,0x3f7f4e6d,0xbd96a905,0x3f7f2f9d,0xbda3308c,0x3f7f0e58,0xbdafb680,0x3f7eea9d,0xbdbc3ac3,
0x3f7853f8,0xbe78cfcc,0x3f764d97,0xbe8b9507,0x3f740bdd,0xbe9aa086,0x3f718f57,0xbea986c4,0x3f6ed89e,0xbeb8442a,0x3f6be858,0xbec6d529,0x3f68bf3c,0xbed53641,0x3f655e0b,0xbee363fa,
0x3f7ec46d,0xbdc8bd36,0x3f7e70b0,0xbde1bc2e,0x3f7e1324,0xbdfab273,0x3f7dabcc,0xbe09cf86,0x3f7d3aac,0xbe164083,0x3f7cbfc9,0xbe22abb6,0x3f7c3b28,0xbe2f10a2,0x3f7baccd,0xbe3b6ecf,
0x3f74fa0b,0xbe94a031,0x3f721352,0xbea68f12,0x3f6ed89e,0xbeb8442a,0x3f6b4b0c,0xbec9b953,0x3f676bd8,0xbedae880,0x3f633c5a,0xbeebcbbb,0x3f5ebe05,0xbefc5d27,0x3f59f26a,0xbf064b82,
0x3f7d3aac,0xbe164083,0x3f7c7eb0,0xbe28defc,0x3f7baccd,0xbe3b6ecf,0x3f7ac516,0xbe4dee60,0x3f79c79d,0xbe605c13,0x3f78b47b,0xbe72b651,0x3f778bc5,0xbe827dc0,0x3f764d97,0xbe8b9507,
0x3f710908,0xbeac7cd4,0x3f6d1c1d,0xbec1071e,0x3f68bf3c,0xbed53641,0x3f63f473,0xbee900b7,0x3f5ebe05,0xbefc5d27,0x3f591e6a,0xbf07a136,0x3f531849,0xbf10d3cd,0x3f4cae79,0xbf19c200,
0x3f6c835e,0xbec3ef15,0x3f676bd8,0xbedae880,0x3f61c598,0xbef15aea,0x3f5b941a,0xbf039c3d,0x3f54db31,0xbf0e39da,0x3f4d9f02,0xbf187fc0,0x3f45e403,0xbf226799,0x3f3daef9,0xbf2beb4a,
0x3f54db31,0xbf0e39da,0x3f49d112,0xbf1d7fd1,0x3f3daef9,0xbf2beb4a,0x3f3085bb,0xbf396842,0x3f226799,0xbf45e403,0x3f13682a,0xbf514d3d,0x3f039c3d,0xbf5b941a,0x3ee63375,0xbf64aa59,
0x3f676bd8,0xbedae880,0x3f6106f2,0xbef41f07,0x3f59f26a,0xbf064b82,0x3f5233c6,0xbf121eb0,0x3f49d112,0xbf1d7fd1,0x3f40d0da,0xbf286605,0x3f373a23,0xbf32c8c9,0x3f2d1469,0xbf3ca003,
0x3f4d9f02,0xbf187fc0,0x3f40d0da,0xbf286605,0x3f32c8c9,0xbf373a23,0x3f239da9,0xbf44e3f5,0x3f13682a,0xbf514d3d,0x3f0242b1,0xbf5c61c7,0x3ee0924f,0xbf660f88,0x3ebb31a0,0xbf6e46be,
0x3f61c598,0xbef15aea,0x3f59f26a,0xbf064b82,0x3f514d3d,0xbf13682a,0x3f47de65,0xbf1ff6cb,0x3f3daef9,0xbf2beb4a,0x3f32c8c9,0xbf373a23,0x3f273656,0xbf41d870,0x3f1b02c6,0xbf4bbbf8,
0x3f45e403,0xbf226799,0x3f373a23,0xbf32c8c9,0x3f273656,0xbf41d870,0x3f15f6d9,0xbf4f7a1f,0x3f039c3d,0xbf5b941a,0x3ee0924f,0xbf660f88,0x3eb8442a,0xbf6ed89e,0x3e8e9a22,0xbf75dec6,
0x3f5b941a,0xbf039c3d,0x3f5233c6,0xbf121eb0,0x3f47de65,0xbf1ff6cb,0x3f3ca003,0xbf2d1469,0x3f3085bb,0xbf396842,0x3f239da9,0xbf44e3f5,0x3f15f6d9,0xbf4f7a1f,0x3f07a136,0xbf591e6a,
0x3f3daef9,0xbf2beb4a,0x3f2d1469,0xbf3ca003,0x3f1b02c6,0xbf4bbbf8,0x3f07a136,0xbf591e6a,0x3ee63375,0xbf64aa59,0x3ebb31a0,0xbf6e46be,0x3e8e9a22,0xbf75dec6,0x3e419b37,0xbf7b61fc,
0x3f3504f3,0xbf3504f3,0x3f226799,0xbf45e403,0x3f0e39da,0xbf54db31,0x3ef15aea,0xbf61c598,0x3ec3ef15,0xbf6c835e,0x3e94a031,0xbf74fa0b,0x3e47c5c2,0xbf7b14be,0x3dc8bd36,0xbf7ec46d,
0x3f0e39da,0xbf54db31,0x3ee63375,0xbf64aa59,0x3eac7cd4,0xbf710908,0x3e605c13,0xbf79c79d,0x3dc8bd36,0xbf7ec46d,0xbcc90ab0,0xbf7fec43,0xbe164083,0xbf7d3aac,0xbe888e93,0xbf76ba07,
0x3f2beb4a,0xbf3daef9,0x3f173c07,0xbf4e8d90,0x3f00e7e4,0xbf5d2d53,0x3ed25a09,0xbf696591,0x3ea09ae5,0xbf731447,0x3e5a3997,0xbf7a1e84,0x3de1bc2e,0xbf7e70b0,0x3bc90f88,0xbf7ffec4,
0x3f039c3d,0xbf5b941a,0x3ecc9b8b,0xbf6aab7b,0x3e8e9a22,0xbf75dec6,0x3e1c76de,0xbf7cfe73,0x3cc90ab0,0xbf7fec43,0xbdd53db9,0xbf7e9bc9,0xbe6c9a7f,0xbf791298,0xbeb554ec,0xbf6f6830,
0x3f226799,0xbf45e403,0x3f0b9a6b,0xbf5695e5,0x3ee63375,0xbf64aa59,0x3eb263ef,0xbf6ff573,0x3e78cfcc,0xbf7853f8,0x3e09cf86,0xbf7dabcc,0x3cc90ab0,0xbf7fec43,0xbdafb680,0xbf7f0e58,
0x3ef15aea,0xbf61c598,0x3eb263ef,0xbf6ff573,0x3e605c13,0xbf79c79d,0x3dafb680,0xbf7f0e58,0xbd48fb30,0xbf7fb10f,0xbe3b6ecf,0xbf7baccd,0xbea09ae5,0xbf731447,0xbee0924f,0xbf660f88,
0x3f187fc0,0xbf4d9f02,0x3eff17b2,0xbf5df6be,0x3ec9b953,0xbf6b4b0c,0x3e919ddd,0xbf756d97,0x3e2f10a2,0xbf7c3b28,0x3d621469,0xbf7f9c18,0xbd7b2b74,0xbf7f84ab,0xbe354098,0xbf7bf531,
0x3edae880,0xbf676bd8,0x3e97a117,0xbf748422,0x3e22abb6,0xbf7cbfc9,0x3c96c9b6,0xbf7ff4e6,0xbdfab273,0xbf7e1324,0xbe8586ce,0xbf772417,0xbec9b953,0xbf6b4b0c,0xbf04f484,0xbf5ac450,
0x3ec3ef15,0xbf6c835e,0x3e78cfcc,0xbf7853f8,0x3dc8bd36,0xbf7ec46d,0xbd48fb30,0xbf7fb10f,0xbe47c5c2,0xbf7b14be,0xbeac7cd4,0xbf710908,0xbef15aea,0xbf61c598,0xbf187fc0,0xbf4d9f02,
0x3e47c5c2,0xbf7b14be,0x3cc90ab0,0xbf7fec43,0xbe164083,0xbf7d3aac,0xbea09ae5,0xbf731447,0xbef15aea,0xbf61c598,0xbf1d7fd1,0xbf49d112,0xbf3daef9,0xbf2beb4a,0xbf584853,0xbf08f59b,
0x3eac7cd4,0xbf710908,0x3e419b37,0xbf7b61fc,0x3d16c32c,0xbf7fd397,0xbdee3876,0xbf7e4323,0xbe888e93,0xbf76ba07,0xbed25a09,0xbf696591,0xbf0b9a6b,0xbf5695e5,0xbf2ac082,0xbf3ebc1b,
0x3e164083,0xbf7d3aac,0xbcfb49ba,0xbf7fe129,0xbe541501,0xbf7a7302,0xbec1071e,0xbf6d1c1d,0xbf08f59b,0xbf584853,0xbf2d1469,0xbf3ca003,0xbf4bbbf8,0xbf1b02c6,0xbf63f473,0xbee900b7,
0x3e94a031,0xbf74fa0b,0x3e09cf86,0xbf7dabcc,0xbcc90ab0,0xbf7fec43,0xbe3b6ecf,0xbf7baccd,0xbeac7cd4,0xbf710908,0xbef6e0cb,0xbf604621,0xbf1d7fd1,0xbf49d112,0xbf3b8f3b,0xbf2e3bde,
0x3dc8bd36,0xbf7ec46d,0xbdafb680,0xbf7f0e58,0xbe888e93,0xbf76ba07,0xbee0924f,0xbf660f88,0xbf187fc0,0xbf4d9f02,0xbf3b8f3b,0xbf2e3bde,0xbf584853,0xbf08f59b,0xbf6db293,0xbebe1d4a,
0x3e78cfcc,0xbf7853f8,0x3da3308c,0xbf7f2f9d,0xbdafb680,0xbf7f0e58,0xbe7ee6e1,0xbf77f110,0xbecf7bca,0xbf6a09a7,0xbf0cead0,0xbf55b993,0xbf2e3bde,0xbf3b8f3b,0xbf4ac77f,0xbf1c420c,
0x3d48fb30,0xbf7fb10f,0xbe1008b7,0xbf7d7474,0xbea68f12,0xbf721352,0xbeff17b2,0xbf5df6be,0xbf273656,0xbf41d870,0xbf48d8b3,0xbf1ebc12,0xbf633c5a,0xbeebcbbb,0xbf756d97,0xbe919ddd,
0x3f800000,0x0,0x3f800000,0x0,0x3f800000,0x0,0x3f800000,0x0,0x3f800000,0x0,0x3f800000,0x0,0x3f800000,0x0,0x3f800000,0x0,
0x3f6c835e,0xbec3ef15,0x3f6a09a7,0xbecf7bca,0x3f676bd8,0xbedae880,0x3f64aa59,0xbee63375,0x3f61c598,0xbef15aea,0x3f5ebe05,0xbefc5d27,0x3f5b941a,0xbf039c3d,0x3f584853,0xbf08f59b,
0x3f7ec46d,0xbdc8bd36,0x3f7e9bc9,0xbdd53db9,0x3f7e70b0,0xbde1bc2e,0x3f7e4323,0xbdee3876,0x3f7e1324,0xbdfab273,0x3f7de0b1,0xbe039502,0x3f7dabcc,0xbe09cf86,0x3f7d7474,0xbe1008b7,
0x3f61c598,0xbef15aea,0x3f5df6be,0xbeff17b2,0x3f59f26a,0xbf064b82,0x3f55b993,0xbf0cead0,0x3f514d3d,0xbf13682a,0x3f4cae79,0xbf19c200,0x3f47de65,0xbf1ff6cb,0x3f42de29,0xbf26050a,
0x3f7b14be,0xbe47c5c2,0x3f7a7302,0xbe541501,0x3f79c79d,0xbe605c13,0x3f791298,0xbe6c9a7f,0x3f7853f8,0xbe78cfcc,0x3f778bc5,0xbe827dc0,0x3f76ba07,0xbe888e93,0x3f75dec6,0xbe8e9a22,
0x3f54db31,0xbf0e39da,0x3f4f7a1f,0xbf15f6d9,0x3f49d112,0xbf1d7fd1,0x3f43e200,0xbf24d225,0x3f3daef9,0xbf2beb4a,0x3f373a23,0xbf32c8c9,0x3f3085bb,0xbf396842,0x3f299415,0xbf3fc767,
0x3f74fa0b,0xbe94a031,0x3f73913f,0xbe9d9e78,0x3f721352,0xbea68f12,0x3f708066,0xbeaf713a,0x3f6ed89e,0xbeb8442a,0x3f6d1c1d,0xbec1071e,0x3f6b4b0c,0xbec9b953,0x3f696591,0xbed25a09,
0x3f45e403,0xbf226799,0x3f3ebc1b,0xbf2ac082,0x3f373a23,0xbf32c8c9,0x3f2f61a5,0xbf3a7ca4,0x3f273656,0xbf41d870,0x3f1ebc12,0xbf48d8b3,0x3f15f6d9,0xbf4f7a1f,0x3f0cead0,0xbf55b993,
0x3f3504f3,0xbf3504f3,0x3f2beb4a,0xbf3daef9,0x3f226799,0xbf45e403,0x3f187fc0,0xbf4d9f02,0x3f0e39da,0xbf54db31,0x3f039c3d,0xbf5b941a,0x3ef15aea,0xbf61c598,0x3edae880,0xbf676bd8,
0x3ec3ef15,0xbf6c835e,0x3ea09ae5,0xbf731447,0x3e78cfcc,0xbf7853f8,0x3e2f10a2,0xbf7c3b28,0x3dc8bd36,0xbf7ec46d,0x3cc90ab0,0xbf7fec43,0xbd48fb30,0xbf7fb10f,0xbdfab273,0xbf7e1324,
0x3f226799,0xbf45e403,0x3f173c07,0xbf4e8d90,0x3f0b9a6b,0xbf5695e5,0x3eff17b2,0xbf5df6be,0x3ee63375,0xbf64aa59,0x3ecc9b8b,0xbf6aab7b,0x3eb263ef,0xbf6ff573,0x3e97a117,0xbf748422,
0x3e94a031,0xbf74fa0b,0x3e5a3997,0xbf7a1e84,0x3e09cf86,0xbf7dabcc,0x3d621469,0xbf7f9c18,0xbcc90ab0,0xbf7fec43,0xbdd53db9,0xbf7e9bc9,0xbe3b6ecf,0xbf7baccd,0xbe8586ce,0xbf772417,
0x3f0e39da,0xbf54db31,0x3f00e7e4,0xbf5d2d53,0x3ee63375,0xbf64aa59,0x3ec9b953,0xbf6b4b0c,0x3eac7cd4,0xbf710908,0x3e8e9a22,0xbf75dec6,0x3e605c13,0xbf79c79d,0x3e22abb6,0xbf7cbfc9,
0x3e47c5c2,0xbf7b14be,0x3de1bc2e,0xbf7e70b0,0x3cc90ab0,0xbf7fec43,0xbd7b2b74,0xbf7f84ab,0xbe164083,0xbf7d3aac,0xbe6c9a7f,0xbf791298,0xbea09ae5,0xbf731447,0xbec9b953,0xbf6b4b0c,
0x3ef15aea,0xbf61c598,0x3ed25a09,0xbf696591,0x3eb263ef,0xbf6ff573,0x3e919ddd,0xbf756d97,0x3e605c13,0xbf79c79d,0x3e1c76de,0xbf7cfe73,0x3dafb680,0xbf7f0e58,0x3c96c9b6,0xbf7ff4e6,
0x3dc8bd36,0xbf7ec46d,0x3bc90f88,0xbf7ffec4,0xbdafb680,0xbf7f0e58,0xbe354098,0xbf7bf531,0xbe888e93,0xbf76ba07,0xbeb554ec,0xbf6f6830,0xbee0924f,0xbf660f88,0xbf04f484,0xbf5ac450,
0x0,0xbf800000,0xbdc8bd36,0xbf7ec46d,0xbe47c5c2,0xbf7b14be,0xbe94a031,0xbf74fa0b,0xbec3ef15,0xbf6c835e,0xbef15aea,0xbf61c598,0xbf0e39da,0xbf54db31,0xbf226799,0xbf45e403,
0xbec3ef15,0xbf6c835e,0xbefc5d27,0xbf5ebe05,0xbf187fc0,0xbf4d9f02,0xbf3085bb,0xbf396842,0xbf45e403,0xbf226799,0xbf584853,0xbf08f59b,0xbf676bd8,0xbedae880,0xbf731447,0xbea09ae5,
0xbdc8bd36,0xbf7ec46d,0xbe4dee60,0xbf7ac516,0xbe9aa086,0xbf740bdd,0xbecc9b8b,0xbf6aab7b,0xbefc5d27,0xbf5ebe05,0xbf14b039,0xbf5064af,0xbf299415,0xbf3fc767,0xbf3ca003,0xbf2d1469,
0xbef15aea,0xbf61c598,0xbf14b039,0xbf5064af,0xbf2e3bde,0xbf3b8f3b,0xbf44e3f5,0xbf239da9,0xbf584853,0xbf08f59b,0xbf6816a8,0xbed8106b,0xbf740bdd,0xbe9aa086,0xbf7bf531,0xbe354098,
0xbe47c5c2,0xbf7b14be,0xbe9aa086,0xbf740bdd,0xbecf7bca,0xbf6a09a7,0xbf00e7e4,0xbf5d2d53,0xbf187fc0,0xbf4d9f02,0xbf2e3bde,0xbf3b8f3b,0xbf41d870,0xbf273656,0xbf531849,0xbf10d3cd,
0xbf0e39da,0xbf54db31,0xbf299415,0xbf3fc767,0xbf41d870,0xbf273656,0xbf5695e5,0xbf0b9a6b,0xbf676bd8,0xbedae880,0xbf740bdd,0xbe9aa086,0xbf7c3b28,0xbe2f10a2,0xbf7fd397,0xbd16c32c,
0xbe94a031,0xbf74fa0b,0xbecc9b8b,0xbf6aab7b,0xbf00e7e4,0xbf5d2d53,0xbf19c200,0xbf4cae79,0xbf3085bb,0xbf396842,0xbf44e3f5,0xbf239da9,0xbf5695e5,0xbf0b9a6b,0xbf655e0b,0xbee363fa,
0xbf226799,0xbf45e403,0xbf3ca003,0xbf2d1469,0xbf531849,0xbf10d3cd,0xbf655e0b,0xbee363fa,0xbf731447,0xbea09ae5,0xbf7bf531,0xbe354098,0xbf7fd397,0xbd16c32c,0xbf7e9bc9,0x3dd53db9,
0xbf3504f3,0xbf3504f3,0xbf4d9f02,0xbf187fc0,0xbf61c598,0xbef15aea,0xbf710908,0xbeac7cd4,0xbf7b14be,0xbe47c5c2,0xbf7fb10f,0xbd48fb30,0xbf7ec46d,0x3dc8bd36,0xbf7853f8,0x3e78cfcc,
0xbf6c835e,0xbec3ef15,0xbf79c79d,0xbe605c13,0xbf7fb10f,0xbd48fb30,0xbf7e1324,0x3dfab273,0xbf74fa0b,0x3e94a031,0xbf64aa59,0x3ee63375,0xbf4d9f02,0x3f187fc0,0xbf3085bb,0x3f396842,
0xbf45e403,0xbf226799,0xbf5c61c7,0xbf0242b1,0xbf6db293,0xbebe1d4a,0xbf796e4e,0xbe667c66,0xbf7f4e6d,0xbd96a905,0xbf7f2f9d,0x3da3308c,0xbf791298,0x3e6c9a7f,0xbf6d1c1d,0x3ec1071e,
0xbf74fa0b,0xbe94a031,0xbf7e4323,0xbdee3876,0xbf7f84ab,0x3d7b2b74,0xbf78b47b,0x3e72b651,0xbf6a09a7,0x3ecf7bca,0xbf53fac3,0x3f0f8784,0xbf373a23,0x3f32c8c9,0xbf14b039,0x3f5064af,
0xbf54db31,0xbf0e39da,0xbf68bf3c,0xbed53641,0xbf76ba07,0xbe888e93,0xbf7e70b0,0xbde1bc2e,0xbf7fb10f,0x3d48fb30,0xbf7a7302,0x3e541501,0xbf6ed89e,0x3eb8442a,0xbf5d2d53,0x3f00e7e4,
0xbf7b14be,0xbe47c5c2,0xbf7ffb11,0xbc490e90,0xbf7c3b28,0x3e2f10a2,0xbf6ff573,0x3eb263ef,0xbf5b941a,0x3f039c3d,0xbf3fc767,0x3f299415,0xbf1d7fd1,0x3f49d112,0xbeebcbbb,0x3f633c5a,
0xbf61c598,0xbef15aea,0xbf7294f8,0xbea395c5,0xbf7cbfc9,0xbe22abb6,0xbf7ffec4,0x3bc90f88,0xbf7c3b28,0x3e2f10a2,0xbf718f57,0x3ea986c4,0xbf604621,0x3ef6e0cb,0xbf48d8b3,0x3f1ebc12,
0xbf7ec46d,0xbdc8bd36,0xbf7eea9d,0x3dbc3ac3,0xbf75dec6,0x3e8e9a22,0xbf63f473,0x3ee900b7,0xbf49d112,0x3f1d7fd1,0xbf286605,0x3f40d0da,0xbf00e7e4,0x3f5d2d53,0xbea986c4,0x3f718f57,
0x3f800000,0x0,0x3f800000,0x0,0x3f800000,0x0,0x3f800000,0x0,0x3f800000,0x0,0x3f800000,0x0,0x3f800000,0x0,0x3f800000,0x0,
0x3f54db31,0xbf0e39da,0x3f514d3d,0xbf13682a,0x3f4d9f02,0xbf187fc0,0x3f49d112,0xbf1d7fd1,0x3f45e403,0xbf226799,0x3f41d870,0xbf273656,0x3f3daef9,0xbf2beb4a,0x3f396842,0xbf3085bb,
0x3f7d3aac,0xbe164083,0x3f7cfe73,0xbe1c76de,0x3f7cbfc9,0xbe22abb6,0x3f7c7eb0,0xbe28defc,0x3f7c3b28,0xbe2f10a2,0x3f7bf531,0xbe354098,0x3f7baccd,0xbe3b6ecf,0x3f7b61fc,0xbe419b37,
0x3f3daef9,0xbf2beb4a,0x3f385216,0xbf31a81d,0x3f32c8c9,0xbf373a23,0x3f2d1469,0xbf3ca003,0x3f273656,0xbf41d870,0x3f212ff9,0xbf46e22a,0x3f1b02c6,0xbf4bbbf8,0x3f14b039,0xbf5064af,
0x3f74fa0b,0xbe94a031,0x3f740bdd,0xbe9aa086,0x3f731447,0xbea09ae5,0x3f721352,0xbea68f12,0x3f710908,0xbeac7cd4,0x3f6ff573,0xbeb263ef,0x3f6ed89e,0xbeb8442a,0x3f6db293,0xbebe1d4a,
0x3f226799,0xbf45e403,0x3f1b02c6,0xbf4bbbf8,0x3f13682a,0xbf514d3d,0x3f0b9a6b,0xbf5695e5,0x3f039c3d,0xbf5b941a,0x3ef6e0cb,0xbf604621,0x3ee63375,0xbf64aa59,0x3ed53641,0xbf68bf3c,
0x3f676bd8,0xbedae880,0x3f655e0b,0xbee363fa,0x3f633c5a,0xbeebcbbb,0x3f6106f2,0xbef41f07,0x3f5ebe05,0xbefc5d27,0x3f5c61c7,0xbf0242b1,0x3f59f26a,0xbf064b82,0x3f577026,0xbf0a48ad,
0x3f039c3d,0xbf5b941a,0x3ef41f07,0xbf6106f2,0x3ee0924f,0xbf660f88,0x3ecc9b8b,0xbf6aab7b,0x3eb8442a,0xbf6ed89e,0x3ea395c5,0xbf7294f8,0x3e8e9a22,0xbf75dec6,0x3e72b651,0xbf78b47b,
0x3ec3ef15,0xbf6c835e,0x3eac7cd4,0xbf710908,0x3e94a031,0xbf74fa0b,0x3e78cfcc,0xbf7853f8,0x3e47c5c2,0xbf7b14be,0x3e164083,0xbf7d3aac,0x3dc8bd36,0xbf7ec46d,0x3d48fb30,0xbf7fb10f,
0xbe47c5c2,0xbf7b14be,0xbe888e93,0xbf76ba07,0xbeac7cd4,0xbf710908,0xbecf7bca,0xbf6a09a7,0xbef15aea,0xbf61c598,0xbf08f59b,0xbf584853,0xbf187fc0,0xbf4d9f02,0xbf273656,0xbf41d870,
0x3e78cfcc,0xbf7853f8,0x3e419b37,0xbf7b61fc,0x3e09cf86,0xbf7dabcc,0x3da3308c,0xbf7f2f9d,0x3cc90ab0,0xbf7fec43,0xbcfb49ba,0xbf7fe129,0xbdafb680,0xbf7f0e58,0xbe1008b7,0xbf7d7474,
0xbeac7cd4,0xbf710908,0xbed25a09,0xbf696591,0xbef6e0cb,0xbf604621,0xbf0cead0,0xbf55b993,0xbf1d7fd1,0xbf49d112,0xbf2d1469,0xbf3ca003,0xbf3b8f3b,0xbf2e3bde,0xbf48d8b3,0xbf1ebc12,
0x3dc8bd36,0xbf7ec46d,0x3d16c32c,0xbf7fd397,0xbcc90ab0,0xbf7fec43,0xbdafb680,0xbf7f0e58,0xbe164083,0xbf7d3aac,0xbe541501,0xbf7a7302,0xbe888e93,0xbf76ba07,0xbea68f12,0xbf721352,
0xbef15aea,0xbf61c598,0xbf0b9a6b,0xbf5695e5,0xbf1d7fd1,0xbf49d112,0xbf2e3bde,0xbf3b8f3b,0xbf3daef9,0xbf2beb4a,0xbf4bbbf8,0xbf1b02c6,0xbf584853,0xbf08f59b,0xbf633c5a,0xbeebcbbb,
0xbd48fb30,0xbf7fb10f,0xbdee3876,0xbf7e4323,0xbe3b6ecf,0xbf7baccd,0xbe7ee6e1,0xbf77f110,0xbea09ae5,0xbf731447,0xbec1071e,0xbf6d1c1d,0xbee0924f,0xbf660f88,0xbeff17b2,0xbf5df6be,
0xbf187fc0,0xbf4d9f02,0xbf2ac082,0xbf3ebc1b,0xbf3b8f3b,0xbf2e3bde,0xbf4ac77f,0xbf1c420c,0xbf584853,0xbf08f59b,0xbf63f473,0xbee900b7,0xbf6db293,0xbebe1d4a,0xbf756d97,0xbe919ddd,
0xbf3504f3,0xbf3504f3,0xbf45e403,0xbf226799,0xbf54db31,0xbf0e39da,0xbf61c598,0xbef15aea,0xbf6c835e,0xbec3ef15,0xbf74fa0b,0xbe94a031,0xbf7b14be,0xbe47c5c2,0xbf7ec46d,0xbdc8bd36,
0xbf7b14be,0xbe47c5c2,0xbf7f4e6d,0xbd96a905,0xbf7fb10f,0x3d48fb30,0xbf7c3b28,0x3e2f10a2,0xbf74fa0b,0x3e94a031,0xbf6a09a7,0x3ecf7bca,0xbf5b941a,0x3f039c3d,0xbf49d112,0x3f1d7fd1,
0xbf4d9f02,0xbf187fc0,0xbf5c61c7,0xbf0242b1,0xbf68bf3c,0xbed53641,0xbf7294f8,0xbea395c5,0xbf79c79d,0xbe605c13,0xbf7e4323,0xbdee3876,0xbf7ffb11,0xbc490e90,0xbf7eea9d,0x3dbc3ac3,
0xbf7fb10f,0xbd48fb30,0xbf7f2f9d,0x3da3308c,0xbf7a7302,0x3e541501,0xbf718f57,0x3ea986c4,0xbf64aa59,0x3ee63375,0xbf53fac3,0x3f0f8784,0xbf3fc767,0x3f299415,0xbf286605,0x3f40d0da,
0xbf61c598,0xbef15aea,0xbf6db293,0xbebe1d4a,0xbf76ba07,0xbe888e93,0xbf7cbfc9,0xbe22abb6,0xbf7fb10f,0xbd48fb30,0xbf7f84ab,0x3d7b2b74,0xbf7c3b28,0x3e2f10a2,0xbf75dec6,0x3e8e9a22,
0xbf7ec46d,0x3dc8bd36,0xbf791298,0x3e6c9a7f,0xbf6ed89e,0x3eb8442a,0xbf604621,0x3ef6e0cb,0xbf4d9f02,0x3f187fc0,0xbf373a23,0x3f32c8c9,0xbf1d7fd1,0x3f49d112,0xbf00e7e4,0x3f5d2d53,
0xbf710908,0xbeac7cd4,0xbf796e4e,0xbe667c66,0xbf7e70b0,0xbde1bc2e,0xbf7ffec4,0x3bc90f88,0xbf7e1324,0x3dfab273,0xbf78b47b,0x3e72b651,0xbf6ff573,0x3eb263ef,0xbf63f473,0x3ee900b7,
0xbf7853f8,0x3e78cfcc,0xbf6d1c1d,0x3ec1071e,0xbf5d2d53,0x3f00e7e4,0xbf48d8b3,0x3f1ebc12,0xbf3085bb,0x3f396842,0xbf14b039,0x3f5064af,0xbeebcbbb,0x3f633c5a,0xbea986c4,0x3f718f57,
0xbf6c835e,0x3ec3ef15,0xbf5b941a,0x3f039c3d,0xbf45e403,0x3f226799,0xbf2beb4a,0x3f3daef9,0xbf0e39da,0x3f54db31,0xbedae880,0x3f676bd8,0xbe94a031,0x3f74fa0b,0xbe164083,0x3f7d3aac,
0xbf0e39da,0x3f54db31,0xbecf7bca,0x3f6a09a7,0xbe78cfcc,0x3f7853f8,0xbd96a905,0x3f7f4e6d,0x3dc8bd36,0x3f7ec46d,0x3e888e93,0x3f76ba07,0x3edae880,0x3f676bd8,0x3f13682a,0x3f514d3d,
0xbf5b941a,0x3f039c3d,0xbf44e3f5,0x3f239da9,0xbf299415,0x3f3fc767,0xbf0a48ad,0x3f577026,0xbecf7bca,0x3f6a09a7,0xbe8586ce,0x3f772417,0xbde1bc2e,0x3f7e70b0,0x3d2fe007,0x3f7fc38f,
0xbedae880,0x3f676bd8,0xbe8586ce,0x3f772417,0xbdafb680,0x3f7f0e58,0x3dbc3ac3,0x3f7eea9d,0x3e888e93,0x3f76ba07,0x3eddbe79,0x3f66becc,0x3f15f6d9,0x3f4f7a1f,0x3f385216,0x3f31a81d,
0xbf45e403,0x3f226799,0xbf299415,0x3f3fc767,0xbf08f59b,0x3f584853,0xbec9b953,0x3f6b4b0c,0xbe78cfcc,0x3f7853f8,0xbdafb680,0x3f7f0e58,0x3d96a905,0x3f7f4e6d,0x3e6c9a7f,0x3f791298,
0xbe94a031,0x3f74fa0b,0xbde1bc2e,0x3f7e70b0,0x3d96a905,0x3f7f4e6d,0x3e827dc0,0x3f778bc5,0x3edae880,0x3f676bd8,0x3f15f6d9,0x3f4f7a1f,0x3f396842,0x3f3085bb,0x3f5695e5,0x3f0b9a6b,
0xbf2beb4a,0x3f3daef9,0xbf0a48ad,0x3f577026,0xbec9b953,0x3f6b4b0c,0xbe72b651,0x3f78b47b,0xbd96a905,0x3f7f4e6d,0x3dbc3ac3,0x3f7eea9d,0x3e827dc0,0x3f778bc5,0x3ed25a09,0x3f696591,
0xbe164083,0x3f7d3aac,0x3d2fe007,0x3f7fc38f,0x3e6c9a7f,0x3f791298,0x3ed25a09,0x3f696591,0x3f13682a,0x3f514d3d,0x3f385216,0x3f31a81d,0x3f5695e5,0x3f0b9a6b,0x3f6d1c1d,0x3ec1071e,
0x3e00,0x3e00,0x3e00,0x3e00,0x3e00,0x3e00,0x3e00,0x3e00,0x3e00,0x3e00,0x3e00,0x3e00,0x3e00,0x3e00,0x3e00,0x3e00,
0xbd443ded,0xbcc83dfb,0xbc493dff,0xbd153df5,0xbdb53db5,0xbdd53d8e,0xbdc63da2,0xbde23d71,0xbe000000,0xbdfbbcc8,0xbdffbc49,0xbdf5bd15,0xbdb5bdb5,0xbd8ebdd5,0xbda2bdc6,0xbd71bde2,
0xbdb53db5,0xbd443ded,0xbcc83dfb,0xbd8e3dd5,0xbe000000,0xbdedbd44,0xbdfbbcc8,0xbdd5bd8e,0xbe00,0x3d44bded,0x3cc8bdfb,0x3d8ebdd5,0x3e000000,0x3ded3d44,0x3dfb3cc8,0x3dd53d8e,
0xbded3d44,0xbd8e3dd5,0xbd153df5,0xbdc63da2,0xbdb5bdb5,0xbcc8bdfb,0xbd71bde2,0x3c49bdff,0x3e000000,0x3dd53d8e,0x3df53d15,0x3da23dc6,0xbdb53db5,0xbdfb3cc8,0xbde23d71,0xbdffbc49,
0xbe000000,0xbdb53db5,0xbd443ded,0xbded3d44,0xbe00,0x3db5bdb5,0x3d44bded,0x3dedbd44,0x3e00,0xbdb53db5,0xbd443ded,0xbded3d44,0xbe00,0x3db5bdb5,0x3d44bded,0x3dedbd44,
0xbdedbd44,0xbdd53d8e,0xbd713de2,0xbdff3c49,0x3db5bdb5,0x3dfb3cc8,0x3df5bd15,0x3dc63da2,0xbe000000,0xbd8ebdd5,0xbde2bd71,0xbc49bdff,0x3db53db5,0xbcc83dfb,0x3d153df5,0xbda23dc6,
0xbdb5bdb5,0xbded3d44,0xbd8e3dd5,0xbdfbbcc8,0x3e000000,0x3d443ded,0x3dd53d8e,0xbcc83dfb,0xbe00,0x3dedbd44,0x3d8ebdd5,0x3dfb3cc8,0xbe000000,0xbd44bded,0xbdd5bd8e,0x3cc8bdfb,
0xbd44bded,0xbdfb3cc8,0xbda23dc6,0xbde2bd71,0x3db53db5,0xbd8e3dd5,0x3c493dff,0xbdf53d15,0x3e000000,0x3cc83dfb,0x3dc63da2,0xbd713de2,0x3db5bdb5,0x3dd53d8e,0x3dffbc49,0x3d153df5,
0xbe00,0xbe000000,0xbdb53db5,0xbdb5bdb5,0x3e00,0xbe000000,0xbdb53db5,0xbdb5bdb5,0x3e00,0xbe000000,0xbdb53db5,0xbdb5bdb5,0x3e00,0xbe000000,0xbdb53db5,0xbdb5bdb5,
0x3d44bded,0xbdfbbcc8,0xbdc63da2,0xbd71bde2,0xbdb53db5,0xbd8ebdd5,0xbdffbc49,0x3d15bdf5,0xbe000000,0x3cc8bdfb,0xbda2bdc6,0x3de2bd71,0xbdb5bdb5,0x3dd5bd8e,0x3c49bdff,0x3df53d15,
0x3db5bdb5,0xbdedbd44,0xbdd53d8e,0xbcc8bdfb,0xbe000000,0x3d44bded,0xbd8ebdd5,0x3dfbbcc8,0xbe00,0x3ded3d44,0x3dd5bd8e,0x3cc83dfb,0x3e000000,0xbd443ded,0x3d8e3dd5,0xbdfb3cc8,
0x3dedbd44,0xbdd5bd8e,0xbde23d71,0x3c49bdff,0xbdb5bdb5,0x3dfbbcc8,0x3d15bdf5,0x3da23dc6,0x3e000000,0xbd8e3dd5,0x3d713de2,0xbdffbc49,0xbdb53db5,0xbcc8bdfb,0xbdf5bd15,0x3dc6bda2,
0x3e000000,0xbdb5bdb5,0xbded3d44,0x3d44bded,0xbe00,0x3db53db5,0x3dedbd44,0xbd443ded,0x3e00,0xbdb5bdb5,0xbded3d44,0x3d44bded,0xbe00,0x3db53db5,0x3dedbd44,0xbd443ded,
0x3ded3d44,0xbd8ebdd5,0xbdf53d15,0x3da2bdc6,0x3db5bdb5,0xbcc83dfb,0x3de23d71,0xbdff3c49,0xbe000000,0x3dd5bd8e,0xbd15bdf5,0x3dc63da2,0x3db53db5,0xbdfbbcc8,0xbd713de2,0xbc49bdff,
0x3db53db5,0xbd44bded,0xbdfb3cc8,0x3dd5bd8e,0x3e000000,0xbded3d44,0x3cc83dfb,0xbd8ebdd5,0xbe00,0x3d443ded,0x3dfbbcc8,0xbdd53d8e,0xbe000000,0x3dedbd44,0xbcc8bdfb,0x3d8e3dd5,
0x3d443ded,0xbcc8bdfb,0xbdff3c49,0x3df5bd15,0x3db53db5,0xbdd5bd8e,0xbda23dc6,0x3d71bde2,0x3e000000,0xbdfb3cc8,0x3c493dff,0xbd15bdf5,0x3db5bdb5,0xbd8e3dd5,0x3dc63da2,0xbde2bd71,
0x3e00,0xbe00,0xbe000000,0x3e000000,0x3e00,0xbe00,0xbe000000,0x3e000000,0x3e00,0xbe00,0xbe000000,0x3e000000,0x3e00,0xbe00,0xbe000000,0x3e000000,
0xbd443ded,0x3cc8bdfb,0xbdffbc49,0x3df53d15,0xbdb53db5,0x3dd5bd8e,0xbda2bdc6,0x3d713de2,0xbe000000,0x3dfb3cc8,0x3c49bdff,0xbd153df5,0xbdb5bdb5,0x3d8e3dd5,0x3dc6bda2,0xbde23d71,
0xbdb53db5,0x3d44bded,0xbdfbbcc8,0x3dd53d8e,0xbe000000,0x3ded3d44,0x3cc8bdfb,0xbd8e3dd5,0xbe00,0xbd443ded,0x3dfb3cc8,0xbdd5bd8e,0x3e000000,0xbdedbd44,0xbcc83dfb,0x3d8ebdd5,
0xbded3d44,0x3d8ebdd5,0xbdf5bd15,0x3da23dc6,0xbdb5bdb5,0x3cc83dfb,0x3de2bd71,0xbdffbc49,0x3e000000,0xbdd5bd8e,0xbd153df5,0x3dc6bda2,0xbdb53db5,0x3dfbbcc8,0xbd71bde2,0xbc493dff,
0xbe000000,0x3db5bdb5,0xbdedbd44,0x3d443ded,0xbe00,0xbdb53db5,0x3ded3d44,0xbd44bded,0x3e00,0x3db5bdb5,0xbdedbd44,0x3d443ded,0xbe00,0xbdb53db5,0x3ded3d44,0xbd44bded,
0xbdedbd44,0x3dd5bd8e,0xbde2bd71,0x3c493dff,0x3db5bdb5,0xbdfbbcc8,0x3d153df5,0x3da2bdc6,0xbe000000,0x3d8e3dd5,0x3d71bde2,0xbdff3c49,0x3db53db5,0x3cc8bdfb,0xbdf53d15,0x3dc63da2,
0xbdb5bdb5,0x3dedbd44,0xbdd5bd8e,0xbcc83dfb,0x3e000000,0xbd44bded,0xbd8e3dd5,0x3dfb3cc8,0xbe00,0xbded3d44,0x3dd53d8e,0x3cc8bdfb,0xbe000000,0x3d443ded,0x3d8ebdd5,0xbdfbbcc8,
0xbd44bded,0x3dfbbcc8,0xbdc6bda2,0xbd713de2,0x3db53db5,0x3d8ebdd5,0xbdff3c49,0x3d153df5,0x3e000000,0xbcc8bdfb,0xbda23dc6,0x3de23d71,0x3db5bdb5,0xbdd5bd8e,0x3c493dff,0x3df5bd15,
0xbe00,0x3e000000,0xbdb5bdb5,0xbdb53db5,0x3e00,0x3e000000,0xbdb5bdb5,0xbdb53db5,0x3e00,0x3e000000,0xbdb5bdb5,0xbdb53db5,0x3e00,0x3e000000,0xbdb5bdb5,0xbdb53db5,
0x3d44bded,0x3dfb3cc8,0xbda2bdc6,0xbde23d71,0xbdb53db5,0x3d8e3dd5,0x3c49bdff,0xbdf5bd15,0xbe000000,0xbcc83dfb,0x3dc6bda2,0xbd71bde2,0xbdb5bdb5,0xbdd53d8e,0x3dff3c49,0x3d15bdf5,
0x3db5bdb5,0x3ded3d44,0xbd8ebdd5,0xbdfb3cc8,0xbe000000,0xbd443ded,0x3dd5bd8e,0xbcc8bdfb,0xbe00,0xbdedbd44,0x3d8e3dd5,0x3dfbbcc8,0x3e000000,0x3d44bded,0xbdd53d8e,0x3cc83dfb,
0x3dedbd44,0x3dd53d8e,0xbd71bde2,0xbdffbc49,0xbdb5bdb5,0xbdfb3cc8,0x3df53d15,0x3dc6bda2,0x3e000000,0x3d8ebdd5,0xbde23d71,0xbc493dff,0xbdb53db5,0x3cc83dfb,0x3d15bdf5,0xbda2bdc6,
0x3e000000,0x3db53db5,0xbd44bded,0xbdedbd44,0xbe00,0xbdb5bdb5,0x3d443ded,0x3ded3d44,0x3e00,0x3db53db5,0xbd44bded,0xbdedbd44,0xbe00,0xbdb5bdb5,0x3d443ded,0x3ded3d44,
0x3ded3d44,0x3d8e3dd5,0xbd15bdf5,0xbdc6bda2,0x3db5bdb5,0x3cc8bdfb,0xbd713de2,0x3c493dff,0xbe000000,0xbdd53d8e,0x3df5bd15,0x3da2bdc6,0x3db53db5,0x3dfb3cc8,0xbde2bd71,0xbdff3c49,
0x3db53db5,0x3d443ded,0xbcc8bdfb,0xbd8ebdd5,0x3e000000,0x3dedbd44,0xbdfb3cc8,0xbdd53d8e,0xbe00,0xbd44bded,0x3cc83dfb,0x3d8e3dd5,0xbe000000,0xbded3d44,0x3dfbbcc8,0x3dd5bd8e,
0x3d443ded,0x3cc83dfb,0xbc49bdff,0xbd15bdf5,0x3db53db5,0x3dd53d8e,0xbdc6bda2,0xbde2bd71,0x3e000000,0x3dfbbcc8,0xbdff3c49,0xbdf53d15,0x3db5bdb5,0x3d8ebdd5,0xbda23dc6,0xbd713de2,
0x3d803d80,0x3e00,0x3e00,0x3e00,0x3e00,0x3e00,0x3e00,0x3e00,0x3e00,0x3e00,0x3e00,0x3e00,0x3e00,0x3e00,0x3e00,0x3e00,
0xbd803d80,0x3cc8bdfb,0x3c49bdff,0x3d15bdf5,0xbded3d44,0x3dd5bd8e,0x3dc6bda2,0x3de2bd71,0xbdedbd44,0x3dfb3cc8,0x3dff3c49,0x3df53d15,0xbd44bded,0x3d8e3dd5,0x3da23dc6,0x3d713de2,
0x3d803d80,0xbd443ded,0xbcc83dfb,0xbd8e3dd5,0xbdb5bdb5,0xbdedbd44,0xbdfbbcc8,0xbdd5bd8e,0x3db5bdb5,0x3d44bded,0x3cc8bdfb,0x3d8ebdd5,0x3db53db5,0x3ded3d44,0x3dfb3cc8,0x3dd53d8e,
0xbd803d80,0x3d8ebdd5,0x3d15bdf5,0x3dc6bda2,0x3d44bded,0x3cc83dfb,0x3d713de2,0xbc493dff,0x3d443ded,0xbdd5bd8e,0xbdf5bd15,0xbda2bdc6,0xbdedbd44,0x3dfbbcc8,0x3de2bd71,0x3dff3c49,
0x3d803d80,0xbdb53db5,0xbd443ded,0xbded3d44,0x3e000000,0x3db5bdb5,0x3d44bded,0x3dedbd44,0xbe000000,0xbdb53db5,0xbd443ded,0xbded3d44,0x3e000000,0x3db5bdb5,0x3d44bded,0x3dedbd44,
0xbd803d80,0x3dd5bd8e,0x3d71bde2,0x3dffbc49,0x3d443ded,0xbdfbbcc8,0xbdf53d15,0xbdc6bda2,0x3d44bded,0x3d8e3dd5,0x3de23d71,0x3c493dff,0xbded3d44,0x3cc8bdfb,0xbd15bdf5,0x3da2bdc6,
0x3d803d80,0xbded3d44,0xbd8e3dd5,0xbdfbbcc8,0xbdb53db5,0x3d443ded,0x3dd53d8e,0xbcc83dfb,0x3db53db5,0x3dedbd44,0x3d8ebdd5,0x3dfb3cc8,0x3db5bdb5,0xbd44bded,0xbdd5bd8e,0x3cc8bdfb,
0xbd803d80,0x3dfbbcc8,0x3da2bdc6,0x3de23d71,0xbdedbd44,0x3d8ebdd5,0xbc49bdff,0x3df5bd15,0xbded3d44,0xbcc8bdfb,0xbdc6bda2,0x3d71bde2,0xbd443ded,0xbdd5bd8e,0xbdff3c49,0xbd15bdf5,
0x3d803d80,0xbe000000,0xbdb53db5,0xbdb5bdb5,0xbe00,0xbe000000,0xbdb53db5,0xbdb5bdb5,0xbe00,0xbe000000,0xbdb53db5,0xbdb5bdb5,0xbe00,0xbe000000,0xbdb53db5,0xbdb5bdb5,
0xbd803d80,0x3dfb3cc8,0x3dc6bda2,0x3d713de2,0x3dedbd44,0x3d8e3dd5,0x3dff3c49,0xbd153df5,0x3ded3d44,0xbcc83dfb,0x3da23dc6,0xbde23d71,0x3d443ded,0xbdd53d8e,0xbc493dff,0xbdf5bd15,
0x3d803d80,0xbdedbd44,0xbdd53d8e,0xbcc8bdfb,0x3db53db5,0x3d44bded,0xbd8ebdd5,0x3dfbbcc8,0xbdb53db5,0x3ded3d44,0x3dd5bd8e,0x3cc83dfb,0xbdb5bdb5,0xbd443ded,0x3d8e3dd5,0xbdfb3cc8,
0xbd803d80,0x3dd53d8e,0x3de2bd71,0xbc493dff,0xbd443ded,0xbdfb3cc8,0xbd153df5,0xbda2bdc6,0xbd44bded,0x3d8ebdd5,0xbd71bde2,0x3dff3c49,0x3ded3d44,0x3cc83dfb,0x3df53d15,0xbdc63da2,
0x3d803d80,0xbdb5bdb5,0xbded3d44,0x3d44bded,0xbe000000,0x3db53db5,0x3dedbd44,0xbd443ded,0x3e000000,0xbdb5bdb5,0xbded3d44,0x3d44bded,0xbe000000,0x3db53db5,0x3dedbd44,0xbd443ded,
0xbd803d80,0x3d8e3dd5,0x3df5bd15,0xbda23dc6,0xbd44bded,0x3cc8bdfb,0xbde2bd71,0x3dffbc49,0xbd443ded,0xbdd53d8e,0x3d153df5,0xbdc6bda2,0x3dedbd44,0x3dfb3cc8,0x3d71bde2,0x3c493dff,
0x3d803d80,0xbd44bded,0xbdfb3cc8,0x3dd5bd8e,0x3db5bdb5,0xbded3d44,0x3cc83dfb,0xbd8ebdd5,0xbdb5bdb5,0x3d443ded,0x3dfbbcc8,0xbdd53d8e,0xbdb53db5,0x3dedbd44,0xbcc8bdfb,0x3d8e3dd5,
0xbd803d80,0x3cc83dfb,0x3dffbc49,0xbdf53d15,0x3ded3d44,0x3dd53d8e,0x3da2bdc6,0xbd713de2,0x3dedbd44,0x3dfbbcc8,0xbc49bdff,0x3d153df5,0x3d44bded,0x3d8ebdd5,0xbdc6bda2,0x3de23d71,
0x3d803d80,0xbe00,0xbe000000,0x3e000000,0x3e00,0xbe00,0xbe000000,0x3e000000,0x3e00,0xbe00,0xbe000000,0x3e000000,0x3e00,0xbe00,0xbe000000,0x3e000000,
0xbd803d80,0xbcc83dfb,0x3dff3c49,0xbdf5bd15,0xbded3d44,0xbdd53d8e,0x3da23dc6,0xbd71bde2,0xbdedbd44,0xbdfbbcc8,0xbc493dff,0x3d15bdf5,0xbd44bded,0xbd8ebdd5,0xbdc63da2,0x3de2bd71,
0x3d803d80,0x3d44bded,0xbdfbbcc8,0x3dd53d8e,0xbdb5bdb5,0x3ded3d44,0x3cc8bdfb,0xbd8e3dd5,0x3db5bdb5,0xbd443ded,0x3dfb3cc8,0xbdd5bd8e,0x3db53db5,0xbdedbd44,0xbcc83dfb,0x3d8ebdd5,
0xbd803d80,0xbd8e3dd5,0x3df53d15,0xbda2bdc6,0x3d44bded,0xbcc8bdfb,0xbde23d71,0x3dff3c49,0x3d443ded,0x3dd53d8e,0x3d15bdf5,0xbdc63da2,0xbdedbd44,0xbdfb3cc8,0x3d713de2,0x3c49bdff,
0x3d803d80,0x3db5bdb5,0xbdedbd44,0x3d443ded,0x3e000000,0xbdb53db5,0x3ded3d44,0xbd44bded,0xbe000000,0x3db5bdb5,0xbdedbd44,0x3d443ded,0x3e000000,0xbdb53db5,0x3ded3d44,0xbd44bded,
0xbd803d80,0xbdd53d8e,0x3de23d71,0xbc49bdff,0x3d443ded,0x3dfb3cc8,0xbd15bdf5,0xbda23dc6,0x3d44bded,0xbd8ebdd5,0xbd713de2,0x3dffbc49,0xbded3d44,0xbcc83dfb,0x3df5bd15,0xbdc6bda2,
0x3d803d80,0x3dedbd44,0xbdd5bd8e,0xbcc83dfb,0xbdb53db5,0xbd44bded,0xbd8e3dd5,0x3dfb3cc8,0x3db53db5,0xbded3d44,0x3dd53d8e,0x3cc8bdfb,0x3db5bdb5,0x3d443ded,0x3d8ebdd5,0xbdfbbcc8,
0xbd803d80,0xbdfb3cc8,0x3dc63da2,0x3d71bde2,0xbdedbd44,0xbd8e3dd5,0x3dffbc49,0xbd15bdf5,0xbded3d44,0x3cc83dfb,0x3da2bdc6,0xbde2bd71,0xbd443ded,0x3dd53d8e,0xbc49bdff,0xbdf53d15,
0x3d803d80,0x3e000000,0xbdb5bdb5,0xbdb53db5,0xbe00,0x3e000000,0xbdb5bdb5,0xbdb53db5,0xbe00,0x3e000000,0xbdb5bdb5,0xbdb53db5,0xbe00,0x3e000000,0xbdb5bdb5,0xbdb53db5,
0xbd803d80,0xbdfbbcc8,0x3da23dc6,0x3de2bd71,0x3dedbd44,0xbd8ebdd5,0xbc493dff,0x3df53d15,0x3ded3d44,0x3cc8bdfb,0xbdc63da2,0x3d713de2,0x3d443ded,0x3dd5bd8e,0xbdffbc49,0xbd153df5,
0x3d803d80,0x3ded3d44,0xbd8ebdd5,0xbdfb3cc8,0x3db53db5,0xbd443ded,0x3dd5bd8e,0xbcc8bdfb,0xbdb53db5,0xbdedbd44,0x3d8e3dd5,0x3dfbbcc8,0xbdb5bdb5,0x3d44bded,0xbdd53d8e,0x3cc83dfb,
0xbd803d80,0xbdd5bd8e,0x3d713de2,0x3dff3c49,0xbd443ded,0x3dfbbcc8,0xbdf5bd15,0xbdc63da2,0xbd44bded,0xbd8e3dd5,0x3de2bd71,0x3c49bdff,0x3ded3d44,0xbcc8bdfb,0xbd153df5,0x3da23dc6,
0x3d803d80,0x3db53db5,0xbd44bded,0xbdedbd44,0xbe000000,0xbdb5bdb5,0x3d443ded,0x3ded3d44,0x3e000000,0x3db53db5,0xbd44bded,0xbdedbd44,0xbe000000,0xbdb5bdb5,0x3d443ded,0x3ded3d44,
0xbd803d80,0xbd8ebdd5,0x3d153df5,0x3dc63da2,0xbd44bded,0xbcc83dfb,0x3d71bde2,0xbc49bdff,0xbd443ded,0x3dd5bd8e,0xbdf53d15,0xbda23dc6,0x3dedbd44,0xbdfbbcc8,0x3de23d71,0x3dffbc49,
0x3d803d80,0x3d443ded,0xbcc8bdfb,0xbd8ebdd5,0x3db5bdb5,0x3dedbd44,0xbdfb3cc8,0xbdd53d8e,0xbdb5bdb5,0xbd44bded,0x3cc83dfb,0x3d8e3dd5,0xbdb53db5,0xbded3d44,0x3dfbbcc8,0x3dd5bd8e,
0xbd803d80,0xbcc8bdfb,0x3c493dff,0x3d153df5,0x3ded3d44,0xbdd5bd8e,0x3dc63da2,0x3de23d71,0x3dedbd44,0xbdfb3cc8,0x3dffbc49,0x3df5bd15,0x3d44bded,0xbd8e3dd5,0x3da2bdc6,0x3d71bde2,
0xbc493dff,0xbbc93e00,0xbb493e00,0xbc173dff,0xbcc83dfb,0xbcf93df8,0xbce03dfa,0xbd093df7,0xbd443ded,0xbd5b3de7,0xbd4f3dea,0xbd663de5,0xbd8e3dd5,0xbd983dce,0xbd933dd1,0xbd9d3dca,
0xbd713de2,0xbcf93df8,0xbc7b3dfe,0xbd383def,0xbdd53d8e,0xbdf13d2c,0xbde53d66,0xbdfa3ce0,0xbdedbd44,0xbdcebd98,0xbddfbd7c,0xbdb9bdb1,0xbcc8bdfb,0x3bc9be00,0xbc17bdff,0x3cafbdfc,
0xbdc63da2,0xbd5b3de7,0xbce03dfa,0xbd9d3dca,0xbdfbbcc8,0xbdcebd98,0xbdeabd4f,0xbda7bdc2,0x3d44bded,0x3dbebdac,0x3d93bdd1,0x3ddfbd7c,0x3dd53d8e,0x3d843ddc,0x3db13db9,0x3d213df3,
0xbdf53d15,0xbd983dce,0xbd213df3,0xbdd13d93,0xbd8ebdd5,0x3bc9be00,0xbd09bdf7,0x3d38bdef,0x3ded3d44,0x3d843ddc,0x3dc23da7,0x3ce03dfa,0xbdfb3cc8,0xbde7bd5b,0xbdfebc7b,0xbdb9bdb1,
0xbdffbc49,0xbdbe3dac,0xbd4f3dea,0xbdf33d21,0x3cc8bdfb,0x3ddcbd84,0x3d93bdd1,0x3dfebc7b,0xbd443ded,0xbdf13d2c,0xbdb93db1,0xbdffbc17,0x3d8ebdd5,0x3dfdbc96,0x3dd8bd89,0x3df73d09,
0xbde2bd71,0xbddc3d84,0xbd7c3ddf,0xbe003b49,0x3dd5bd8e,0x3de73d5b,0x3dffbc17,0x3d933dd1,0xbdedbd44,0xbc96bdfd,0xbd9dbdca,0x3d38bdef,0x3cc83dfb,0xbdbe3dac,0xbd213df3,0xbdfa3ce0,
0xbda2bdc6,0xbdf13d2c,0xbd933dd1,0xbdf7bd09,0x3dfb3cc8,0x3c963dfd,0x3db13db9,0xbd663de5,0x3d44bded,0x3e003bc9,0x3dd8bd89,0x3dca3d9d,0xbdd5bd8e,0x3cf9bdf8,0xbd38bdef,0x3dc2bda7,
0xbd15bdf5,0xbdfd3c96,0xbda73dc2,0xbdd8bd89,0x3d8e3dd5,0xbdbe3dac,0xbc7b3dfe,0xbe003b49,0x3ded3d44,0xbcf93df8,0x3d663de5,0xbdd13d93,0x3dfbbcc8,0x3d2c3df1,0x3ddf3d7c,0xbd383def,
0x3c49bdff,0xbe00bbc9,0xbdb93db1,0xbda7bdc2,0xbcc83dfb,0xbdf8bcf9,0xbdd83d89,0xbd7cbddf,0xbd443ded,0xbde7bd5b,0xbdef3d38,0xbd21bdf3,0xbd8e3dd5,0xbdcebd98,0xbdfc3caf,0xbc7bbdfe,
0x3d71bde2,0xbdf8bcf9,0xbdca3d9d,0xbd4fbdea,0xbdd53d8e,0xbd2cbdf1,0xbdf3bd21,0x3d89bdd8,0xbdedbd44,0x3d98bdce,0xbd09bdf7,0x3e00bb49,0xbcc8bdfb,0x3e003bc9,0x3da7bdc2,0x3d933dd1,
0x3dc6bda2,0xbde7bd5b,0xbdd83d89,0xbc7bbdfe,0xbdfbbcc8,0x3d98bdce,0xbd38bdef,0x3dff3c17,0x3d44bded,0x3dac3dbe,0x3dfcbcaf,0xbd093df7,0x3dd53d8e,0xbddc3d84,0xbb493e00,0xbde5bd66,
0x3df5bd15,0xbdcebd98,0xbde53d66,0x3cafbdfc,0xbd8ebdd5,0x3e003bc9,0x3d7cbddf,0x3d4f3dea,0x3ded3d44,0xbddc3d84,0x3c173dff,0xbdd8bd89,0xbdfb3cc8,0x3d5bbde7,0xbd9dbdca,0x3e00bb49,
0x3dff3c49,0xbdacbdbe,0xbdef3d38,0x3d66bde5,0x3cc8bdfb,0x3d843ddc,0x3dfcbcaf,0xbd9d3dca,0xbd443ded,0xbd2cbdf1,0xbe00bb49,0x3dc2bda7,0x3d8ebdd5,0x3c963dfd,0x3dfa3ce0,0xbddf3d7c,
0x3de23d71,0xbd84bddc,0xbdf73d09,0x3db1bdb9,0x3dd5bd8e,0xbd5b3de7,0x3dc23da7,0xbdfcbcaf,0xbdedbd44,0x3dfdbc96,0x3c7bbdfe,0x3d4f3dea,0x3cc83dfb,0xbdacbdbe,0xbde53d66,0x3d89bdd8,
0x3da23dc6,0xbd2cbdf1,0xbdfc3caf,0x3ddfbd7c,0x3dfb3cc8,0xbdfd3c96,0xbb493e00,0xbd21bdf3,0x3d44bded,0xbbc93e00,0x3dfa3ce0,0xbdfe3c7b,0xbdd5bd8e,0x3df83cf9,0x3d4fbdea,0xbc173dff,
0x3d153df5,0xbc96bdfd,0xbdff3c17,0x3dfabce0,0x3d8e3dd5,0xbdacbdbe,0xbdca3d9d,0x3db1bdb9,0x3ded3d44,0xbdf8bcf9,0xbd213df3,0x3cafbdfc,0x3dfbbcc8,0xbdf13d2c,0x3d093df7,0xbd4fbdea,
0xbc493dff,0x3bc9be00,0xbe00bb49,0x3dff3c17,0xbcc83dfb,0x3cf9bdf8,0xbdfabce0,0x3df73d09,0xbd443ded,0x3d5bbde7,0xbdeabd4f,0x3de53d66,0xbd8e3dd5,0x3d98bdce,0xbdd1bd93,0x3dca3d9d,
0xbd713de2,0x3cf9bdf8,0xbdfebc7b,0x3def3d38,0xbdd53d8e,0x3df1bd2c,0xbd66bde5,0x3ce03dfa,0xbdedbd44,0x3dce3d98,0x3d7cbddf,0xbdb13db9,0xbcc8bdfb,0xbbc93e00,0x3dffbc17,0xbdfcbcaf,
0xbdc63da2,0x3d5bbde7,0xbdfabce0,0x3dca3d9d,0xbdfbbcc8,0x3dce3d98,0x3d4fbdea,0xbdc23da7,0x3d44bded,0xbdbe3dac,0x3dd13d93,0xbd7cbddf,0x3dd53d8e,0xbd84bddc,0xbdb93db1,0x3df3bd21,
0xbdf53d15,0x3d98bdce,0xbdf3bd21,0x3d933dd1,0xbd8ebdd5,0xbbc93e00,0x3df7bd09,0xbdefbd38,0x3ded3d44,0xbd84bddc,0xbda73dc2,0x3dfabce0,0xbdfb3cc8,0x3de73d5b,0x3c7bbdfe,0xbdb13db9,
0xbdffbc49,0x3dbebdac,0xbdeabd4f,0x3d213df3,0x3cc8bdfb,0xbddc3d84,0x3dd13d93,0xbc7bbdfe,0xbd443ded,0x3df1bd2c,0xbdb1bdb9,0xbc173dff,0x3d8ebdd5,0xbdfd3c96,0x3d893dd8,0x3d09bdf7,
0xbde2bd71,0x3ddcbd84,0xbddfbd7c,0x3b493e00,0x3dd5bd8e,0xbde7bd5b,0x3c173dff,0x3dd1bd93,0xbdedbd44,0x3c963dfd,0x3dcabd9d,0xbdefbd38,0x3cc83dfb,0x3dbebdac,0xbdf3bd21,0x3ce03dfa,
0xbda2bdc6,0x3df1bd2c,0xbdd1bd93,0xbd093df7,0x3dfb3cc8,0xbc96bdfd,0xbdb93db1,0x3de53d66,0x3d44bded,0xbe00bbc9,0x3d893dd8,0x3d9dbdca,0xbdd5bd8e,0xbcf93df8,0x3defbd38,0xbda7bdc2,
0xbd15bdf5,0x3dfdbc96,0xbdc2bda7,0xbd893dd8,0x3d8e3dd5,0x3dbebdac,0xbdfebc7b,0x3b493e00,0x3ded3d44,0x3cf9bdf8,0xbde53d66,0x3d933dd1,0x3dfbbcc8,0xbd2cbdf1,0xbd7c3ddf,0x3def3d38,
0x3c49bdff,0x3e003bc9,0xbdb1bdb9,0xbdc23da7,0xbcc83dfb,0x3df83cf9,0xbd89bdd8,0xbddf3d7c,0xbd443ded,0x3de73d5b,0xbd38bdef,0xbdf33d21,0xbd8e3dd5,0x3dce3d98,0xbcafbdfc,0xbdfe3c7b,
0x3d71bde2,0x3df83cf9,0xbd9dbdca,0xbdea3d4f,0xbdd53d8e,0x3d2c3df1,0x3d21bdf3,0xbdd8bd89,0xbdedbd44,0xbd983dce,0x3df7bd09,0xbb49be00,0xbcc8bdfb,0xbe00bbc9,0x3dc23da7,0x3dd1bd93,
0x3dc6bda2,0x3de73d5b,0xbd89bdd8,0xbdfe3c7b,0xbdfbbcc8,0xbd983dce,0x3defbd38,0x3c17bdff,0x3d44bded,0xbdacbdbe,0x3caf3dfc,0x3df73d09,0x3dd53d8e,0x3ddcbd84,0xbe00bb49,0xbd663de5,
0x3df5bd15,0x3dce3d98,0xbd66bde5,0xbdfcbcaf,0xbd8ebdd5,0xbe00bbc9,0x3ddf3d7c,0x3deabd4f,0x3ded3d44,0x3ddcbd84,0xbdff3c17,0xbd893dd8,0xbdfb3cc8,0xbd5b3de7,0x3dcabd9d,0xbb49be00,
0x3dff3c49,0x3dac3dbe,0xbd38bdef,0xbde5bd66,0x3cc8bdfb,0xbd84bddc,0x3caf3dfc,0x3dca3d9d,0xbd443ded,0x3d2c3df1,0x3b49be00,0xbda7bdc2,0x3d8ebdd5,0xbc96bdfd,0xbce03dfa,0x3d7c3ddf,
0x3de23d71,0x3d843ddc,0xbd09bdf7,0xbdb9bdb1,0x3dd5bd8e,0x3d5bbde7,0xbda73dc2,0xbcaf3dfc,0xbdedbd44,0xbdfd3c96,0x3dfe3c7b,0x3deabd4f,0x3cc83dfb,0x3dac3dbe,0xbd66bde5,0xbdd8bd89,
0x3da23dc6,0x3d2c3df1,0xbcafbdfc,0xbd7cbddf,0x3dfb3cc8,0x3dfdbc96,0xbe00bb49,0xbdf33d21,0x3d44bded,0x3bc9be00,0xbce03dfa,0x3c7b3dfe,0xbdd5bd8e,0xbdf8bcf9,0x3dea3d4f,0x3dff3c17,
0x3d153df5,0x3c963dfd,0xbc17bdff,0xbce0bdfa,0x3d8e3dd5,0x3dac3dbe,0xbd9dbdca,0xbdb9bdb1,0x3ded3d44,0x3df83cf9,0xbdf3bd21,0xbdfcbcaf,0x3dfbbcc8,0x3df1bd2c,0xbdf73d09,0xbdea3d4f,
0xbdb53d80,0xbdbe3dac,0xbdb93db1,0xbdc23da7,0xbd153df5,0xbddc3d84,0xbdd83d89,0xbddf3d7c,0xbd713de2,0xbdf13d2c,0xbdef3d38,0xbdf33d21,0xbda23dc6,0xbdfd3c96,0xbdfc3caf,0xbdfe3c7b,
0x3db53d80,0x3ddcbd84,0x3dcabd9d,0x3deabd4f,0xbdff3c49,0x3de73d5b,0x3df33d21,0x3dd83d89,0xbda2bdc6,0x3c963dfd,0x3d093df7,0x3b493e00,0x3d15bdf5,0xbdbe3dac,0xbda73dc2,0xbdd13d93,
0xbdb53d80,0xbdf13d2c,0xbdd83d89,0xbdfe3c7b,0xbd71bde2,0xbc96bdfd,0xbd38bdef,0x3c17bdff,0x3df5bd15,0x3e003bc9,0x3dfcbcaf,0x3df73d09,0x3c493dff,0xbcf93df8,0xbb493e00,0xbd663de5,
0x3db53d80,0x3dfdbc96,0x3de5bd66,0x3dfc3caf,0x3da2bdc6,0xbdbe3dac,0xbd7c3ddf,0xbdea3d4f,0xbc493dff,0x3cf9bdf8,0xbc17bdff,0x3d89bdd8,0xbd71bde2,0x3d2c3df1,0x3d9d3dca,0x3b493e00,
0xbdb53d80,0xbe00bbc9,0xbdef3d38,0xbde5bd66,0x3df53d15,0x3df83cf9,0x3dfcbcaf,0x3dca3d9d,0xbde2bd71,0xbde7bd5b,0xbe00bb49,0xbda7bdc2,0x3dc63da2,0x3dce3d98,0x3dfa3ce0,0x3d7c3ddf,
0x3db53d80,0x3df83cf9,0x3df7bd09,0x3db93db1,0x3c493dff,0xbd2cbdf1,0xbdc2bda7,0x3cafbdfc,0x3dc6bda2,0xbd983dce,0xbc7b3dfe,0xbdea3d4f,0xbdf5bd15,0x3e003bc9,0x3de5bd66,0x3dd83d89,
0xbdb53d80,0xbde7bd5b,0xbdfc3caf,0xbd7cbddf,0xbde23d71,0xbd983dce,0xbb493e00,0xbdf33d21,0x3d153df5,0x3dac3dbe,0x3dfa3ce0,0x3c7b3dfe,0x3dffbc49,0x3ddcbd84,0x3d4fbdea,0x3dff3c17,
0x3db53d80,0x3dce3d98,0x3dffbc17,0x3ce03dfa,0xbdc6bda2,0x3e003bc9,0x3dcabd9d,0x3db93db1,0xbdffbc49,0x3ddcbd84,0x3d21bdf3,0x3dfc3caf,0xbde23d71,0x3d5bbde7,0xbd09bdf7,0x3deabd4f,
0xbdb53d80,0xbdacbdbe,0xbe00bb49,0x3c17bdff,0x3d15bdf5,0xbd84bddc,0xbdfabce0,0x3d09bdf7,0x3d71bde2,0xbd2cbdf1,0xbdeabd4f,0x3d66bde5,0x3da2bdc6,0xbc96bdfd,0xbdd1bd93,0x3d9dbdca,
0x3db53d80,0x3d843ddc,0x3dfe3c7b,0xbd383def,0x3dffbc49,0xbd5b3de7,0x3d663de5,0xbdfa3ce0,0x3da23dc6,0xbdfd3c96,0xbd7c3ddf,0xbdb9bdb1,0xbd153df5,0xbdacbdbe,0xbdff3c17,0x3cafbdfc,
0xbdb53d80,0xbd2cbdf1,0xbdfabce0,0x3d9dbdca,0x3d713de2,0x3dfdbc96,0x3d4fbdea,0x3da73dc2,0xbdf53d15,0xbbc93e00,0x3dd13d93,0xbddf3d7c,0xbc49bdff,0xbdf8bcf9,0xbdb93db1,0xbd21bdf3,
0x3db53d80,0x3c963dfd,0x3df33d21,0xbdd13d93,0xbda23dc6,0xbdacbdbe,0xbdf73d09,0x3d38bdef,0x3c49bdff,0x3df83cf9,0x3da7bdc2,0x3ce03dfa,0x3d713de2,0xbdf13d2c,0xbc7b3dfe,0xbdb9bdb1,
0xbdb53d80,0x3bc9be00,0xbdeabd4f,0x3df3bd21,0xbdf5bd15,0xbcf93df8,0x3dd13d93,0xbdfe3c7b,0x3de23d71,0x3d5bbde7,0xbdb1bdb9,0x3dff3c17,0xbdc6bda2,0xbd983dce,0x3d893dd8,0xbdf7bd09,
0x3db53d80,0xbcf93df8,0x3ddf3d7c,0xbe003b49,0xbc49bdff,0x3df1bd2c,0xbc17bdff,0x3d933dd1,0xbdc63da2,0xbdcebd98,0xbdca3d9d,0x3d38bdef,0x3df53d15,0xbbc93e00,0x3df33d21,0xbdfa3ce0,
0xbdb53d80,0x3d5bbde7,0xbdd1bd93,0x3df73d09,0x3de2bd71,0xbdcebd98,0xbdb93db1,0x3d66bde5,0xbd15bdf5,0xbdbe3dac,0x3d893dd8,0xbdcabd9d,0xbdff3c49,0x3d843ddc,0x3defbd38,0xbdc23da7,
0x3db53d80,0xbd983dce,0x3dc23da7,0xbdd8bd89,0x3dc63da2,0xbbc93e00,0x3dfe3c7b,0xbe003b49,0x3dff3c49,0x3d843ddc,0x3de5bd66,0xbdd13d93,0x3de2bd71,0x3de73d5b,0x3d7cbddf,0xbd383def,
0xbdb53d80,0x3dbebdac,0xbdb1bdb9,0x3da73dc2,0xbd153df5,0x3ddcbd84,0xbd89bdd8,0x3d7c3ddf,0xbd713de2,0x3df1bd2c,0xbd38bdef,0x3d213df3,0xbda23dc6,0x3dfdbc96,0xbcafbdfc,0x3c7b3dfe,
0x3db53d80,0xbddc3d84,0x3d9d3dca,0xbd4fbdea,0xbdff3c49,0xbde7bd5b,0xbd213df3,0x3d89bdd8,0xbda2bdc6,0xbc96bdfd,0xbdf73d09,0x3e00bb49,0x3d15bdf5,0x3dbebdac,0xbdc2bda7,0x3d933dd1,
0xbdb53d80,0x3df1bd2c,0xbd89bdd8,0x3c7b3dfe,0xbd71bde2,0x3c963dfd,0x3defbd38,0xbdffbc17,0x3df5bd15,0xbe00bbc9,0x3caf3dfc,0x3d09bdf7,0x3c493dff,0x3cf9bdf8,0xbe00bb49,0x3de53d66,
0x3db53d80,0xbdfd3c96,0x3d663de5,0x3cafbdfc,0x3da2bdc6,0x3dbebdac,0xbddfbd7c,0x3d4f3dea,0xbc493dff,0xbcf93df8,0x3dffbc17,0xbdd8bd89,0xbd71bde2,0xbd2cbdf1,0xbdca3d9d,0x3e00bb49,
0xbdb53d80,0x3e003bc9,0xbd38bdef,0xbd663de5,0x3df53d15,0xbdf8bcf9,0x3caf3dfc,0x3d9dbdca,0xbde2bd71,0x3de73d5b,0x3b49be00,0xbdc23da7,0x3dc63da2,0xbdcebd98,0xbce03dfa,0x3ddfbd7c,
0x3db53d80,0xbdf8bcf9,0x3d093df7,0x3db1bdb9,0x3c493dff,0x3d2c3df1,0x3da7bdc2,0xbdfcbcaf,0x3dc6bda2,0x3d98bdce,0xbdfebc7b,0x3d4f3dea,0xbdf5bd15,0xbe00bbc9,0x3d663de5,0x3d89bdd8,
0xbdb53d80,0x3de73d5b,0xbcafbdfc,0xbddf3d7c,0xbde23d71,0x3d98bdce,0xbe00bb49,0x3d213df3,0x3d153df5,0xbdacbdbe,0xbce03dfa,0x3dfebc7b,0x3dffbc49,0xbddc3d84,0x3dea3d4f,0x3c17bdff,
0x3db53d80,0xbdcebd98,0x3c173dff,0x3dfabce0,0xbdc6bda2,0xbe00bbc9,0x3d9d3dca,0x3db1bdb9,0xbdffbc49,0xbddc3d84,0x3df33d21,0x3cafbdfc,0xbde23d71,0xbd5b3de7,0x3df7bd09,0xbd4fbdea,
0xbdb53d80,0x3dac3dbe,0x3b49be00,0xbdffbc17,0x3d15bdf5,0x3d843ddc,0x3ce0bdfa,0xbdf7bd09,0x3d71bde2,0x3d2c3df1,0x3d4fbdea,0xbde5bd66,0x3da2bdc6,0x3c963dfd,0x3d93bdd1,0xbdcabd9d,
0x3db53d80,0xbd84bddc,0xbc7b3dfe,0x3def3d38,0x3dffbc49,0x3d5bbde7,0xbde53d66,0x3ce03dfa,0x3da23dc6,0x3dfdbc96,0xbddfbd7c,0xbdb13db9,0xbd153df5,0x3dac3dbe,0xbc17bdff,0xbdfcbcaf,
0xbdb53d80,0x3d2c3df1,0x3ce0bdfa,0xbdcabd9d,0x3d713de2,0xbdfd3c96,0x3dea3d4f,0x3dc2bda7,0xbdf53d15,0x3bc9be00,0xbd933dd1,0x3d7c3ddf,0xbc49bdff,0x3df83cf9,0xbdb1bdb9,0xbdf33d21,
0x3db53d80,0xbc96bdfd,0xbd213df3,0x3d933dd1,0xbda23dc6,0x3dac3dbe,0xbd09bdf7,0xbdefbd38,0x3c49bdff,0xbdf8bcf9,0x3dc23da7,0x3dfabce0,0x3d713de2,0x3df1bd2c,0xbdfebc7b,0xbdb13db9,
0xbdb53d80,0xbbc93e00,0x3d4fbdea,0xbd21bdf3,0xbdf5bd15,0x3cf9bdf8,0xbd933dd1,0x3c7b3dfe,0x3de23d71,0xbd5b3de7,0x3db9bdb1,0x3c17bdff,0xbdc6bda2,0x3d98bdce,0xbdd83d89,0xbd093df7,
0x3db53d80,0x3cf9bdf8,0xbd7c3ddf,0x3b493e00,0xbc49bdff,0xbdf13d2c,0x3dffbc17,0x3dd1bd93,0xbdc63da2,0x3dce3d98,0xbd9dbdca,0xbdefbd38,0x3df53d15,0x3bc9be00,0xbd213df3,0x3ce03dfa,
0xbdb53d80,0xbd5b3de7,0x3d93bdd1,0x3d09bdf7,0x3de2bd71,0x3dce3d98,0xbdb1bdb9,0xbde5bd66,0xbd15bdf5,0x3dbebdac,0xbdd83d89,0xbd9d3dca,0xbdff3c49,0xbd84bddc,0x3d383def,0x3da73dc2,
0x3db53d80,0x3d98bdce,0xbda73dc2,0xbd893dd8,0x3dc63da2,0x3bc9be00,0xbc7b3dfe,0x3b493e00,0x3dff3c49,0xbd84bddc,0x3d663de5,0x3d933dd1,0x3de2bd71,0xbde7bd5b,0x3ddf3d7c,0x3def3d38,
0xbcc83dfb,0xbc493dff,0xbbc93e00,0xbc963dfd,0xbd443ded,0xbd713de2,0xbd5b3de7,0xbd843ddc,0xbdb53db5,0xbdc63da2,0xbdbe3dac,0xbdce3d98,0xbded3d44,0xbdf53d15,0xbdf13d2c,0xbdf83cf9,
0xbd8e3dd5,0xbd153df5,0xbc963dfd,0xbd5b3de7,0xbded3d44,0xbdff3c49,0xbdf83cf9,0xbe00bbc9,0xbdb5bdb5,0xbd71bde2,0xbd98bdce,0xbd2cbdf1,0x3d44bded,0x3da2bdc6,0x3d84bddc,0x3dbebdac,
0xbdd53d8e,0xbd713de2,0xbcf93df8,0xbdac3dbe,0xbdedbd44,0xbda2bdc6,0xbdcebd98,0xbd5bbde7,0x3db5bdb5,0x3df5bd15,0x3ddcbd84,0x3e00bbc9,0x3d443ded,0xbc493dff,0x3c963dfd,0xbd2c3df1,
0xbdfb3cc8,0xbda23dc6,0xbd2c3df1,0xbddc3d84,0xbd44bded,0x3d15bdf5,0xbbc9be00,0x3d98bdce,0x3db53db5,0x3c493dff,0x3d5b3de7,0xbcf93df8,0xbdedbd44,0xbd71bde2,0xbdbebdac,0xbc96bdfd,
0xbdfbbcc8,0xbdc63da2,0xbd5b3de7,0xbdf83cf9,0x3d44bded,0x3df5bd15,0x3dbebdac,0x3dfd3c96,0xbdb53db5,0xbdffbc49,0xbdf13d2c,0xbddcbd84,0x3dedbd44,0x3de23d71,0x3e003bc9,0x3d983dce,
0xbdd5bd8e,0xbde23d71,0xbd843ddc,0xbe00bbc9,0x3dedbd44,0x3dc63da2,0x3dfd3c96,0x3d2c3df1,0xbdb5bdb5,0x3d15bdf5,0xbcf9bdf8,0x3dbebdac,0xbd443ded,0xbdff3c49,0xbdce3d98,0xbde7bd5b,
0xbd8ebdd5,0xbdf53d15,0xbd983dce,0xbdf1bd2c,0x3ded3d44,0xbc493dff,0x3d843ddc,0xbdac3dbe,0x3db5bdb5,0x3de23d71,0x3dfdbc96,0x3d5b3de7,0xbd44bded,0x3dc6bda2,0x3cf9bdf8,0x3e00bbc9,
0xbcc8bdfb,0xbdff3c49,0xbdac3dbe,0xbdcebd98,0x3d443ded,0xbde23d71,0xbd2c3df1,0xbdf8bcf9,0x3db53db5,0xbda23dc6,0x3bc93e00,0xbdfd3c96,0x3ded3d44,0xbd153df5,0x3d5b3de7,0xbddc3d84,
0x3cc8bdfb,0xbdffbc49,0xbdbe3dac,0xbd98bdce,0xbd443ded,0xbde2bd71,0xbdf13d2c,0xbcf9bdf8,0xbdb53db5,0xbda2bdc6,0xbe00bbc9,0x3c96bdfd,0xbded3d44,0xbd15bdf5,0xbde7bd5b,0x3d84bddc,
0x3d8ebdd5,0xbdf5bd15,0xbdce3d98,0xbd2cbdf1,0xbded3d44,0xbc49bdff,0xbddcbd84,0x3dbebdac,0xbdb5bdb5,0x3de2bd71,0x3c96bdfd,0x3de73d5b,0x3d44bded,0x3dc63da2,0x3df8bcf9,0xbbc93e00,
0x3dd5bd8e,0xbde2bd71,0xbddc3d84,0xbbc9be00,0xbdedbd44,0x3dc6bda2,0xbc96bdfd,0x3df13d2c,0x3db5bdb5,0x3d153df5,0x3df83cf9,0xbdac3dbe,0x3d443ded,0xbdffbc49,0xbd983dce,0xbd5bbde7,
0x3dfbbcc8,0xbdc6bda2,0xbde73d5b,0x3cf9bdf8,0xbd44bded,0x3df53d15,0x3dacbdbe,0x3c963dfd,0x3db53db5,0xbdff3c49,0xbd2c3df1,0xbd84bddc,0xbdedbd44,0x3de2bd71,0xbbc9be00,0x3dce3d98,
0x3dfb3cc8,0xbda2bdc6,0xbdf13d2c,0x3d84bddc,0x3d44bded,0x3d153df5,0x3e003bc9,0xbdce3d98,0xbdb53db5,0x3c49bdff,0xbde7bd5b,0x3df8bcf9,0x3dedbd44,0xbd713de2,0x3dac3dbe,0xbdfdbc96,
0x3dd53d8e,0xbd71bde2,0xbdf83cf9,0x3dbebdac,0x3dedbd44,0xbda23dc6,0x3d983dce,0xbde7bd5b,0xbdb5bdb5,0x3df53d15,0x3d84bddc,0xbbc93e00,0xbd443ded,0xbc49bdff,0xbdfdbc96,0x3df1bd2c,
0x3d8e3dd5,0xbd15bdf5,0xbdfd3c96,0x3de7bd5b,0x3ded3d44,0xbdffbc49,0xbcf93df8,0xbbc9be00,0x3db5bdb5,0xbd713de2,0x3dce3d98,0xbdf1bd2c,0xbd44bded,0x3da23dc6,0x3ddcbd84,0xbdac3dbe,
0x3cc83dfb,0xbc49bdff,0xbe003bc9,0x3dfdbc96,0x3d443ded,0xbd71bde2,0xbde73d5b,0x3ddcbd84,0x3db53db5,0xbdc6bda2,0xbdac3dbe,0x3d98bdce,0x3ded3d44,0xbdf5bd15,0xbd2c3df1,0x3cf9bdf8,
0xbcc83dfb,0x3c49bdff,0xbe00bbc9,0x3dfd3c96,0xbd443ded,0x3d71bde2,0xbde7bd5b,0x3ddc3d84,0xbdb53db5,0x3dc6bda2,0xbdacbdbe,0x3d983dce,0xbded3d44,0x3df5bd15,0xbd2cbdf1,0x3cf93df8,
0xbd8e3dd5,0x3d15bdf5,0xbdfdbc96,0x3de73d5b,0xbded3d44,0x3dffbc49,0xbcf9bdf8,0xbbc93e00,0xbdb5bdb5,0x3d713de2,0x3dcebd98,0xbdf13d2c,0x3d44bded,0xbda23dc6,0x3ddc3d84,0xbdacbdbe,
0xbdd53d8e,0x3d71bde2,0xbdf8bcf9,0x3dbe3dac,0xbdedbd44,0x3da23dc6,0x3d98bdce,0xbde73d5b,0x3db5bdb5,0xbdf53d15,0x3d843ddc,0xbbc9be00,0x3d443ded,0x3c49bdff,0xbdfd3c96,0x3df13d2c,
0xbdfb3cc8,0x3da2bdc6,0xbdf1bd2c,0x3d843ddc,0xbd44bded,0xbd153df5,0x3e00bbc9,0xbdcebd98,0x3db53db5,0xbc49bdff,0xbde73d5b,0x3df83cf9,0xbdedbd44,0x3d713de2,0x3dacbdbe,0xbdfd3c96,
0xbdfbbcc8,0x3dc6bda2,0xbde7bd5b,0x3cf93df8,0x3d44bded,0xbdf53d15,0x3dac3dbe,0x3c96bdfd,0xbdb53db5,0x3dff3c49,0xbd2cbdf1,0xbd843ddc,0x3dedbd44,0xbde2bd71,0xbbc93e00,0x3dcebd98,
0xbdd5bd8e,0x3de2bd71,0xbddcbd84,0xbbc93e00,0x3dedbd44,0xbdc6bda2,0xbc963dfd,0x3df1bd2c,0xbdb5bdb5,0xbd153df5,0x3df8bcf9,0xbdacbdbe,0xbd443ded,0x3dffbc49,0xbd98bdce,0xbd5b3de7,
0xbd8ebdd5,0x3df5bd15,0xbdcebd98,0xbd2c3df1,0x3ded3d44,0x3c49bdff,0xbddc3d84,0x3dbe3dac,0x3db5bdb5,0xbde2bd71,0x3c963dfd,0x3de7bd5b,0xbd44bded,0xbdc63da2,0x3df83cf9,0xbbc9be00,
0xbcc8bdfb,0x3dffbc49,0xbdbebdac,0xbd983dce,0x3d443ded,0x3de2bd71,0xbdf1bd2c,0xbcf93df8,0x3db53db5,0x3da2bdc6,0xbe003bc9,0x3c963dfd,0x3ded3d44,0x3d15bdf5,0xbde73d5b,0x3d843ddc,
0x3cc8bdfb,0x3dff3c49,0xbdacbdbe,0xbdce3d98,0xbd443ded,0x3de23d71,0xbd2cbdf1,0xbdf83cf9,0xbdb53db5,0x3da23dc6,0x3bc9be00,0xbdfdbc96,0xbded3d44,0x3d153df5,0x3d5bbde7,0xbddcbd84,
0x3d8ebdd5,0x3df53d15,0xbd98bdce,0xbdf13d2c,0xbded3d44,0x3c493dff,0x3d84bddc,0xbdacbdbe,0xbdb5bdb5,0xbde23d71,0x3dfd3c96,0x3d5bbde7,0x3d44bded,0xbdc6bda2,0x3cf93df8,0x3e003bc9,
0x3dd5bd8e,0x3de23d71,0xbd84bddc,0xbe003bc9,0xbdedbd44,0xbdc63da2,0x3dfdbc96,0x3d2cbdf1,0x3db5bdb5,0xbd15bdf5,0xbcf93df8,0x3dbe3dac,0x3d443ded,0x3dff3c49,0xbdcebd98,0xbde73d5b,
0x3dfbbcc8,0x3dc63da2,0xbd5bbde7,0xbdf8bcf9,0xbd44bded,0xbdf5bd15,0x3dbe3dac,0x3dfdbc96,0x3db53db5,0x3dffbc49,0xbdf1bd2c,0xbddc3d84,0xbdedbd44,0xbde23d71,0x3e00bbc9,0x3d98bdce,
0x3dfb3cc8,0x3da23dc6,0xbd2cbdf1,0xbddcbd84,0x3d44bded,0xbd15bdf5,0xbbc93e00,0x3d983dce,0xbdb53db5,0xbc493dff,0x3d5bbde7,0xbcf9bdf8,0x3dedbd44,0x3d71bde2,0xbdbe3dac,0xbc963dfd,
0x3dd53d8e,0x3d713de2,0xbcf9bdf8,0xbdacbdbe,0x3dedbd44,0x3da2bdc6,0xbdce3d98,0xbd5b3de7,0xbdb5bdb5,0xbdf5bd15,0x3ddc3d84,0x3e003bc9,0xbd443ded,0x3c493dff,0x3c96bdfd,0xbd2cbdf1,
0x3d8e3dd5,0x3d153df5,0xbc96bdfd,0xbd5bbde7,0x3ded3d44,0x3dff3c49,0xbdf8bcf9,0xbe003bc9,0x3db5bdb5,0x3d71bde2,0xbd983dce,0xbd2c3df1,0xbd44bded,0xbda2bdc6,0x3d843ddc,0x3dbe3dac,
0x3cc83dfb,0x3c493dff,0xbbc9be00,0xbc96bdfd,0x3d443ded,0x3d713de2,0xbd5bbde7,0xbd84bddc,0x3db53db5,0x3dc63da2,0xbdbebdac,0xbdcebd98,0x3ded3d44,0x3df53d15,0xbdf1bd2c,0xbdf8bcf9,
0xbd803d80,0xbdffbc49,0xbe00bbc9,0xbdfdbc96,0xbd8e3dd5,0xbde2bd71,0xbde7bd5b,0xbddcbd84,0xbdd53d8e,0xbda2bdc6,0xbdacbdbe,0xbd98bdce,0xbdfb3cc8,0xbd15bdf5,0xbd2cbdf1,0xbcf9bdf8,
0x3d803d80,0x3df53d15,0x3dfd3c96,0x3de73d5b,0xbdfbbcc8,0x3c493dff,0x3cf93df8,0xbbc93e00,0xbcc8bdfb,0xbde23d71,0xbdce3d98,0xbdf13d2c,0x3dd5bd8e,0xbdc6bda2,0xbddcbd84,0xbdacbdbe,
0xbd803d80,0xbde2bd71,0xbdf8bcf9,0xbdbebdac,0xbcc8bdfb,0x3dc6bda2,0x3d98bdce,0x3de7bd5b,0x3dfb3cc8,0x3d153df5,0x3d843ddc,0x3bc93e00,0xbd8e3dd5,0xbdffbc49,0xbdfd3c96,0xbdf1bd2c,
0x3d803d80,0x3dc63da2,0x3df13d2c,0x3d843ddc,0x3dd5bd8e,0xbdf5bd15,0xbe003bc9,0xbdcebd98,0xbd8e3dd5,0x3dffbc49,0x3de7bd5b,0x3df83cf9,0x3cc8bdfb,0xbde23d71,0xbdac3dbe,0xbdfd3c96,
0xbd803d80,0xbda2bdc6,0xbde7bd5b,0xbcf9bdf8,0x3dd53d8e,0x3d153df5,0x3dac3dbe,0xbc963dfd,0xbd8ebdd5,0x3c49bdff,0xbd2cbdf1,0x3d84bddc,0x3cc83dfb,0xbd713de2,0xbbc93e00,0xbdce3d98,
0x3d803d80,0x3d713de2,0x3ddc3d84,0xbbc93e00,0xbcc83dfb,0x3da2bdc6,0x3c96bdfd,0x3df1bd2c,0x3dfbbcc8,0xbdf5bd15,0xbdf83cf9,0xbdacbdbe,0xbd8ebdd5,0x3c493dff,0x3d983dce,0xbd5b3de7,
0xbd803d80,0xbd15bdf5,0xbdcebd98,0x3d2cbdf1,0xbdfb3cc8,0xbdffbc49,0xbddc3d84,0xbdbebdac,0xbcc83dfb,0xbd713de2,0x3c963dfd,0xbde73d5b,0x3dd53d8e,0x3da23dc6,0x3df83cf9,0x3bc93e00,
0x3d803d80,0x3c493dff,0x3dbe3dac,0xbd983dce,0xbd8ebdd5,0x3d713de2,0x3df13d2c,0xbcf93df8,0xbdd5bd8e,0x3dc63da2,0x3e00bbc9,0x3c963dfd,0xbdfbbcc8,0x3df53d15,0x3de7bd5b,0x3d843ddc,
0xbd803d80,0x3c49bdff,0xbdacbdbe,0x3dcebd98,0x3d8ebdd5,0x3d71bde2,0xbd2cbdf1,0x3df8bcf9,0x3dd5bd8e,0x3dc6bda2,0x3bc9be00,0x3dfd3c96,0x3dfbbcc8,0x3df5bd15,0x3d5bbde7,0x3ddc3d84,
0x3d803d80,0xbd153df5,0x3d983dce,0xbdf13d2c,0x3dfb3cc8,0xbdff3c49,0xbd843ddc,0xbdacbdbe,0x3cc83dfb,0xbd71bde2,0xbdfdbc96,0x3d5bbde7,0xbdd53d8e,0x3da2bdc6,0xbcf9bdf8,0x3e003bc9,
0xbd803d80,0x3d71bde2,0xbd84bddc,0x3e00bbc9,0x3cc83dfb,0x3da23dc6,0x3dfdbc96,0xbd2c3df1,0xbdfbbcc8,0xbdf53d15,0xbcf93df8,0xbdbebdac,0x3d8ebdd5,0x3c49bdff,0xbdcebd98,0x3de7bd5b,
0x3d803d80,0xbda23dc6,0x3d5b3de7,0xbdf8bcf9,0xbdd53d8e,0x3d15bdf5,0xbdbebdac,0x3dfdbc96,0x3d8ebdd5,0x3c493dff,0x3df13d2c,0xbddc3d84,0xbcc83dfb,0xbd71bde2,0xbe003bc9,0x3d98bdce,
0xbd803d80,0x3dc6bda2,0xbd2cbdf1,0x3ddc3d84,0xbdd5bd8e,0xbdf53d15,0xbbc93e00,0xbd98bdce,0x3d8e3dd5,0x3dff3c49,0x3d5bbde7,0x3cf93df8,0xbcc8bdfb,0xbde2bd71,0xbdbe3dac,0x3c96bdfd,
0x3d803d80,0xbde23d71,0x3cf93df8,0xbdacbdbe,0x3cc8bdfb,0x3dc63da2,0x3dcebd98,0xbd5b3de7,0xbdfb3cc8,0x3d15bdf5,0xbddcbd84,0x3e003bc9,0x3d8e3dd5,0xbdff3c49,0xbc963dfd,0xbd2cbdf1,
0xbd803d80,0x3df5bd15,0xbc96bdfd,0x3d5b3de7,0x3dfbbcc8,0x3c49bdff,0xbdf8bcf9,0x3e00bbc9,0x3cc8bdfb,0xbde2bd71,0xbd983dce,0x3d2cbdf1,0xbdd5bd8e,0xbdc63da2,0x3d843ddc,0xbdbebdac,
0x3d803d80,0xbdff3c49,0x3bc93e00,0xbc96bdfd,0x3d8e3dd5,0xbde23d71,0x3d5b3de7,0xbd84bddc,0x3dd53d8e,0xbda23dc6,0x3dbe3dac,0xbdcebd98,0x3dfb3cc8,0xbd153df5,0x3df13d2c,0xbdf8bcf9,
0xbd803d80,0x3dff3c49,0x3bc9be00,0xbc963dfd,0xbd8e3dd5,0x3de23d71,0x3d5bbde7,0xbd843ddc,0xbdd53d8e,0x3da23dc6,0x3dbebdac,0xbdce3d98,0xbdfb3cc8,0x3d153df5,0x3df1bd2c,0xbdf83cf9,
0x3d803d80,0xbdf5bd15,0xbc963dfd,0x3d5bbde7,0xbdfbbcc8,0xbc49bdff,0xbdf83cf9,0x3e003bc9,0xbcc8bdfb,0x3de2bd71,0xbd98bdce,0x3d2c3df1,0x3dd5bd8e,0x3dc63da2,0x3d84bddc,0xbdbe3dac,
0xbd803d80,0x3de23d71,0x3cf9bdf8,0xbdac3dbe,0xbcc8bdfb,0xbdc63da2,0x3dce3d98,0xbd5bbde7,0x3dfb3cc8,0xbd15bdf5,0xbddc3d84,0x3e00bbc9,0xbd8e3dd5,0x3dff3c49,0xbc96bdfd,0xbd2c3df1,
0x3d803d80,0xbdc6bda2,0xbd2c3df1,0x3ddcbd84,0x3dd5bd8e,0x3df53d15,0xbbc9be00,0xbd983dce,0xbd8e3dd5,0xbdff3c49,0x3d5b3de7,0x3cf9bdf8,0x3cc8bdfb,0x3de2bd71,0xbdbebdac,0x3c963dfd,
0xbd803d80,0x3da23dc6,0x3d5bbde7,0xbdf83cf9,0x3dd53d8e,0xbd15bdf5,0xbdbe3dac,0x3dfd3c96,0xbd8ebdd5,0xbc493dff,0x3df1bd2c,0xbddcbd84,0x3cc83dfb,0x3d71bde2,0xbe00bbc9,0x3d983dce,
0x3d803d80,0xbd71bde2,0xbd843ddc,0x3e003bc9,0xbcc83dfb,0xbda23dc6,0x3dfd3c96,0xbd2cbdf1,0x3dfbbcc8,0x3df53d15,0xbcf9bdf8,0xbdbe3dac,0xbd8ebdd5,0xbc49bdff,0xbdce3d98,0x3de73d5b,
0xbd803d80,0x3d153df5,0x3d98bdce,0xbdf1bd2c,0xbdfb3cc8,0x3dff3c49,0xbd84bddc,0xbdac3dbe,0xbcc83dfb,0x3d71bde2,0xbdfd3c96,0x3d5b3de7,0x3dd53d8e,0xbda2bdc6,0xbcf93df8,0x3e00bbc9,
0x3d803d80,0xbc49bdff,0xbdac3dbe,0x3dce3d98,0xbd8ebdd5,0xbd71bde2,0xbd2c3df1,0x3df83cf9,0xbdd5bd8e,0xbdc6bda2,0x3bc93e00,0x3dfdbc96,0xbdfbbcc8,0xbdf5bd15,0x3d5b3de7,0x3ddcbd84,
0xbd803d80,0xbc493dff,0x3dbebdac,0xbd98bdce,0x3d8ebdd5,0xbd713de2,0x3df1bd2c,0xbcf9bdf8,0x3dd5bd8e,0xbdc63da2,0x3e003bc9,0x3c96bdfd,0x3dfbbcc8,0xbdf53d15,0x3de73d5b,0x3d84bddc,
0x3d803d80,0x3d15bdf5,0xbdce3d98,0x3d2c3df1,0x3dfb3cc8,0x3dffbc49,0xbddcbd84,0xbdbe3dac,0x3cc83dfb,0x3d713de2,0x3c96bdfd,0xbde7bd5b,0xbdd53d8e,0xbda23dc6,0x3df8bcf9,0x3bc9be00,
0xbd803d80,0xbd713de2,0x3ddcbd84,0xbbc9be00,0x3cc83dfb,0xbda2bdc6,0x3c963dfd,0x3df13d2c,0xbdfbbcc8,0x3df5bd15,0xbdf8bcf9,0xbdac3dbe,0x3d8ebdd5,0xbc493dff,0x3d98bdce,0xbd5bbde7,
0x3d803d80,0x3da2bdc6,0xbde73d5b,0xbcf93df8,0xbdd53d8e,0xbd153df5,0x3dacbdbe,0xbc96bdfd,0x3d8ebdd5,0xbc49bdff,0xbd2c3df1,0x3d843ddc,0xbcc83dfb,0x3d713de2,0xbbc9be00,0xbdcebd98,
0xbd803d80,0xbdc63da2,0x3df1bd2c,0x3d84bddc,0xbdd5bd8e,0x3df5bd15,0xbe00bbc9,0xbdce3d98,0x3d8e3dd5,0xbdffbc49,0x3de73d5b,0x3df8bcf9,0xbcc8bdfb,0x3de23d71,0xbdacbdbe,0xbdfdbc96,
0x3d803d80,0x3de2bd71,0xbdf83cf9,0xbdbe3dac,0x3cc8bdfb,0xbdc6bda2,0x3d983dce,0x3de73d5b,0xbdfb3cc8,0xbd153df5,0x3d84bddc,0x3bc9be00,0x3d8e3dd5,0x3dffbc49,0xbdfdbc96,0xbdf13d2c,
0xbd803d80,0xbdf53d15,0x3dfdbc96,0x3de7bd5b,0x3dfbbcc8,0xbc493dff,0x3cf9bdf8,0xbbc9be00,0x3cc8bdfb,0x3de23d71,0xbdcebd98,0xbdf1bd2c,0xbdd5bd8e,0x3dc6bda2,0xbddc3d84,0xbdac3dbe,
0x3d803d80,0x3dffbc49,0xbe003bc9,0xbdfd3c96,0x3d8e3dd5,0x3de2bd71,0xbde73d5b,0xbddc3d84,0x3dd53d8e,0x3da2bdc6,0xbdac3dbe,0xbd983dce,0x3dfb3cc8,0x3d15bdf5,0xbd2c3df1,0xbcf93df8,
0xbd153df5,0xbc963dfd,0xbc173dff,0xbce03dfa,0xbd8e3dd5,0xbdac3dbe,0xbd9d3dca,0xbdb93db1,0xbded3d44,0xbdf83cf9,0xbdf33d21,0xbdfc3caf,0xbdfbbcc8,0xbdf1bd2c,0xbdf7bd09,0xbdeabd4f,
0xbda23dc6,0xbd2c3df1,0xbcaf3dfc,0xbd7c3ddf,0xbdfb3cc8,0xbdfdbc96,0xbe003b49,0xbdf3bd21,0xbd44bded,0xbbc9be00,0xbce0bdfa,0x3c7bbdfe,0x3dd5bd8e,0x3df8bcf9,0x3deabd4f,0x3dffbc17,
0xbde23d71,0xbd843ddc,0xbd093df7,0xbdb93db1,0xbdd5bd8e,0xbd5bbde7,0xbda7bdc2,0xbcafbdfc,0x3dedbd44,0x3dfd3c96,0x3dfebc7b,0x3dea3d4f,0xbcc83dfb,0xbdac3dbe,0xbd663de5,0xbdd83d89,
0xbdff3c49,0xbdac3dbe,0xbd383def,0xbde53d66,0xbcc8bdfb,0x3d84bddc,0x3cafbdfc,0x3dcabd9d,0x3d443ded,0xbd2c3df1,0x3b493e00,0xbda73dc2,0xbd8ebdd5,0x3c96bdfd,0xbce0bdfa,0x3d7cbddf,
0xbdf5bd15,0xbdce3d98,0xbd663de5,0xbdfc3caf,0x3d8ebdd5,0x3e00bbc9,0x3ddfbd7c,0x3dea3d4f,0xbded3d44,0xbddcbd84,0xbdffbc17,0xbd89bdd8,0x3dfb3cc8,0x3d5b3de7,0x3dca3d9d,0xbb493e00,
0xbdc6bda2,0xbde73d5b,0xbd893dd8,0xbdfebc7b,0x3dfbbcc8,0x3d983dce,0x3def3d38,0x3c173dff,0xbd44bded,0x3dacbdbe,0x3cafbdfc,0x3df7bd09,0xbdd53d8e,0xbddcbd84,0xbe003b49,0xbd66bde5,
0xbd71bde2,0xbdf83cf9,0xbd9d3dca,0xbdeabd4f,0x3dd53d8e,0xbd2c3df1,0x3d213df3,0xbdd83d89,0x3dedbd44,0x3d983dce,0x3df73d09,0xbb493e00,0x3cc8bdfb,0x3e00bbc9,0x3dc2bda7,0x3dd13d93,
0xbc49bdff,0xbe003bc9,0xbdb13db9,0xbdc2bda7,0x3cc83dfb,0xbdf83cf9,0xbd893dd8,0xbddfbd7c,0x3d443ded,0xbde73d5b,0xbd383def,0xbdf3bd21,0x3d8e3dd5,0xbdce3d98,0xbcaf3dfc,0xbdfebc7b,
0x3d15bdf5,0xbdfdbc96,0xbdc23da7,0xbd89bdd8,0xbd8e3dd5,0xbdbebdac,0xbdfe3c7b,0x3b49be00,0xbded3d44,0xbcf9bdf8,0xbde5bd66,0x3d93bdd1,0xbdfbbcc8,0x3d2cbdf1,0xbd7cbddf,0x3defbd38,
0x3da2bdc6,0xbdf1bd2c,0xbdd13d93,0xbd09bdf7,0xbdfb3cc8,0x3c96bdfd,0xbdb9bdb1,0x3de5bd66,0xbd44bded,0x3e00bbc9,0x3d89bdd8,0x3d9d3dca,0x3dd5bd8e,0x3cf93df8,0x3def3d38,0xbda73dc2,
0x3de2bd71,0xbddcbd84,0xbddf3d7c,0x3b49be00,0xbdd5bd8e,0x3de7bd5b,0x3c17bdff,0x3dd13d93,0x3dedbd44,0xbc963dfd,0x3dca3d9d,0xbdef3d38,0xbcc83dfb,0xbdbebdac,0xbdf33d21,0x3ce0bdfa,
0x3dffbc49,0xbdbebdac,0xbdea3d4f,0x3d21bdf3,0xbcc8bdfb,0x3ddc3d84,0x3dd1bd93,0xbc7b3dfe,0x3d443ded,0xbdf1bd2c,0xbdb13db9,0xbc17bdff,0xbd8ebdd5,0x3dfd3c96,0x3d89bdd8,0x3d093df7,
0x3df53d15,0xbd98bdce,0xbdf33d21,0x3d93bdd1,0x3d8ebdd5,0x3bc93e00,0x3df73d09,0xbdef3d38,0xbded3d44,0x3d84bddc,0xbda7bdc2,0x3dfa3ce0,0x3dfb3cc8,0xbde73d5b,0x3c7b3dfe,0xbdb1bdb9,
0x3dc63da2,0xbd5bbde7,0xbdfa3ce0,0x3dcabd9d,0x3dfbbcc8,0xbdce3d98,0x3d4f3dea,0xbdc2bda7,0xbd44bded,0x3dbe3dac,0x3dd1bd93,0xbd7c3ddf,0xbdd53d8e,0x3d84bddc,0xbdb9bdb1,0x3df33d21,
0x3d713de2,0xbcf9bdf8,0xbdfe3c7b,0x3defbd38,0x3dd53d8e,0xbdf1bd2c,0xbd663de5,0x3ce0bdfa,0x3dedbd44,0xbdce3d98,0x3d7c3ddf,0xbdb1bdb9,0x3cc8bdfb,0x3bc93e00,0x3dff3c17,0xbdfc3caf,
0x3c493dff,0xbbc9be00,0xbe003b49,0x3dffbc17,0x3cc83dfb,0xbcf9bdf8,0xbdfa3ce0,0x3df7bd09,0x3d443ded,0xbd5bbde7,0xbdea3d4f,0x3de5bd66,0x3d8e3dd5,0xbd98bdce,0xbdd13d93,0x3dcabd9d,
0xbd153df5,0x3c96bdfd,0xbdffbc17,0x3dfa3ce0,0xbd8e3dd5,0x3dacbdbe,0xbdcabd9d,0x3db13db9,0xbded3d44,0x3df8bcf9,0xbd21bdf3,0x3caf3dfc,0xbdfbbcc8,0x3df13d2c,0x3d09bdf7,0xbd4f3dea,
0xbda23dc6,0x3d2cbdf1,0xbdfcbcaf,0x3ddf3d7c,0xbdfb3cc8,0x3dfd3c96,0xbb49be00,0xbd213df3,0xbd44bded,0x3bc93e00,0x3dfabce0,0xbdfebc7b,0x3dd5bd8e,0xbdf83cf9,0x3d4f3dea,0xbc17bdff,
0xbde23d71,0x3d84bddc,0xbdf7bd09,0x3db13db9,0xbdd5bd8e,0x3d5b3de7,0x3dc2bda7,0xbdfc3caf,0x3dedbd44,0xbdfdbc96,0x3c7b3dfe,0x3d4fbdea,0xbcc83dfb,0x3dacbdbe,0xbde5bd66,0x3d893dd8,
0xbdff3c49,0x3dacbdbe,0xbdefbd38,0x3d663de5,0xbcc8bdfb,0xbd843ddc,0x3dfc3caf,0xbd9dbdca,0x3d443ded,0x3d2cbdf1,0xbe003b49,0x3dc23da7,0xbd8ebdd5,0xbc963dfd,0x3dfabce0,0xbddfbd7c,
0xbdf5bd15,0x3dcebd98,0xbde5bd66,0x3caf3dfc,0x3d8ebdd5,0xbe003bc9,0x3d7c3ddf,0x3d4fbdea,0xbded3d44,0x3ddc3d84,0x3c17bdff,0xbdd83d89,0x3dfb3cc8,0xbd5bbde7,0xbd9d3dca,0x3e003b49,
0xbdc6bda2,0x3de7bd5b,0xbdd8bd89,0xbc7b3dfe,0x3dfbbcc8,0xbd98bdce,0xbd383def,0x3dffbc17,0xbd44bded,0xbdac3dbe,0x3dfc3caf,0xbd09bdf7,0xbdd53d8e,0x3ddc3d84,0xbb49be00,0xbde53d66,
0xbd71bde2,0x3df8bcf9,0xbdcabd9d,0xbd4f3dea,0x3dd53d8e,0x3d2cbdf1,0xbdf33d21,0x3d893dd8,0x3dedbd44,0xbd98bdce,0xbd093df7,0x3e003b49,0x3cc8bdfb,0xbe003bc9,0x3da73dc2,0x3d93bdd1,
0xbc49bdff,0x3e00bbc9,0xbdb9bdb1,0xbda73dc2,0x3cc83dfb,0x3df8bcf9,0xbdd8bd89,0xbd7c3ddf,0x3d443ded,0x3de7bd5b,0xbdefbd38,0xbd213df3,0x3d8e3dd5,0x3dcebd98,0xbdfcbcaf,0xbc7b3dfe,
0x3d15bdf5,0x3dfd3c96,0xbda7bdc2,0xbdd83d89,0xbd8e3dd5,0x3dbe3dac,0xbc7bbdfe,0xbe00bb49,0xbded3d44,0x3cf93df8,0x3d66bde5,0xbdd1bd93,0xbdfbbcc8,0xbd2c3df1,0x3ddfbd7c,0xbd38bdef,
0x3da2bdc6,0x3df13d2c,0xbd93bdd1,0xbdf73d09,0xbdfb3cc8,0xbc963dfd,0x3db1bdb9,0xbd66bde5,0xbd44bded,0xbe003bc9,0x3dd83d89,0x3dcabd9d,0x3dd5bd8e,0xbcf9bdf8,0xbd383def,0x3dc23da7,
0x3de2bd71,0x3ddc3d84,0xbd7cbddf,0xbe00bb49,0xbdd5bd8e,0xbde73d5b,0x3dff3c17,0x3d93bdd1,0x3dedbd44,0x3c96bdfd,0xbd9d3dca,0x3d383def,0xbcc83dfb,0x3dbe3dac,0xbd21bdf3,0xbdfabce0,
0x3dffbc49,0x3dbe3dac,0xbd4fbdea,0xbdf3bd21,0xbcc8bdfb,0xbddcbd84,0x3d933dd1,0x3dfe3c7b,0x3d443ded,0x3df13d2c,0xbdb9bdb1,0xbdff3c17,0xbd8ebdd5,0xbdfdbc96,0x3dd83d89,0x3df7bd09,
0x3df53d15,0x3d983dce,0xbd21bdf3,0xbdd1bd93,0x3d8ebdd5,0xbbc9be00,0xbd093df7,0x3d383def,0xbded3d44,0xbd843ddc,0x3dc2bda7,0x3ce0bdfa,0x3dfb3cc8,0x3de7bd5b,0xbdfe3c7b,0xbdb93db1,
0x3dc63da2,0x3d5b3de7,0xbce0bdfa,0xbd9dbdca,0x3dfbbcc8,0x3dcebd98,0xbdea3d4f,0xbda73dc2,0xbd44bded,0xbdbebdac,0x3d933dd1,0x3ddf3d7c,0xbdd53d8e,0xbd843ddc,0x3db1bdb9,0x3d21bdf3,
0x3d713de2,0x3cf93df8,0xbc7bbdfe,0xbd38bdef,0x3dd53d8e,0x3df13d2c,0xbde5bd66,0xbdfabce0,0x3dedbd44,0x3dcebd98,0xbddf3d7c,0xbdb93db1,0x3cc8bdfb,0xbbc9be00,0xbc173dff,0x3caf3dfc,
0x3c493dff,0x3bc93e00,0xbb49be00,0xbc17bdff,0x3cc83dfb,0x3cf93df8,0xbce0bdfa,0xbd09bdf7,0x3d443ded,0x3d5b3de7,0xbd4fbdea,0xbd66bde5,0x3d8e3dd5,0x3d983dce,0xbd93bdd1,0xbd9dbdca,
0xbdb53d80,0xbd98bdce,0xbda7bdc2,0xbd89bdd8,0xbdc63da2,0xbbc9be00,0xbc7bbdfe,0x3b49be00,0xbdff3c49,0x3d84bddc,0x3d66bde5,0x3d93bdd1,0xbde2bd71,0x3de7bd5b,0x3ddfbd7c,0x3defbd38,
0x3db53d80,0x3d5b3de7,0x3d933dd1,0x3d093df7,0xbde2bd71,0xbdce3d98,0xbdb13db9,0xbde53d66,0x3d15bdf5,0xbdbebdac,0xbdd8bd89,0xbd9dbdca,0x3dff3c49,0x3d84bddc,0x3d38bdef,0x3da7bdc2,
0xbdb53d80,0xbcf9bdf8,0xbd7cbddf,0x3b49be00,0x3c49bdff,0x3df13d2c,0x3dff3c17,0x3dd13d93,0x3dc63da2,0xbdce3d98,0xbd9d3dca,0xbdef3d38,0xbdf53d15,0xbbc9be00,0xbd21bdf3,0x3ce0bdfa,
0x3db53d80,0x3bc93e00,0x3d4f3dea,0xbd213df3,0x3df5bd15,0xbcf9bdf8,0xbd93bdd1,0x3c7bbdfe,0xbde23d71,0x3d5b3de7,0x3db93db1,0x3c173dff,0x3dc6bda2,0xbd98bdce,0xbdd8bd89,0xbd09bdf7,
0xbdb53d80,0x3c96bdfd,0xbd21bdf3,0x3d93bdd1,0x3da23dc6,0xbdac3dbe,0xbd093df7,0xbdef3d38,0xbc49bdff,0x3df8bcf9,0x3dc2bda7,0x3dfa3ce0,0xbd713de2,0xbdf1bd2c,0xbdfe3c7b,0xbdb1bdb9,
0x3db53d80,0xbd2c3df1,0x3ce03dfa,0xbdca3d9d,0xbd713de2,0x3dfd3c96,0x3deabd4f,0x3dc23da7,0x3df53d15,0xbbc9be00,0xbd93bdd1,0x3d7cbddf,0x3c49bdff,0xbdf83cf9,0xbdb13db9,0xbdf3bd21,
0xbdb53d80,0x3d84bddc,0xbc7bbdfe,0x3defbd38,0xbdffbc49,0xbd5bbde7,0xbde5bd66,0x3ce0bdfa,0xbda23dc6,0xbdfdbc96,0xbddf3d7c,0xbdb1bdb9,0x3d153df5,0xbdac3dbe,0xbc173dff,0xbdfc3caf,
0x3db53d80,0xbdac3dbe,0x3b493e00,0xbdff3c17,0xbd15bdf5,0xbd843ddc,0x3ce03dfa,0xbdf73d09,0xbd71bde2,0xbd2c3df1,0x3d4f3dea,0xbde53d66,0xbda2bdc6,0xbc963dfd,0x3d933dd1,0xbdca3d9d,
0xbdb53d80,0x3dcebd98,0x3c17bdff,0x3dfa3ce0,0x3dc6bda2,0x3e00bbc9,0x3d9dbdca,0x3db13db9,0x3dffbc49,0x3ddc3d84,0x3df3bd21,0x3caf3dfc,0x3de23d71,0x3d5b3de7,0x3df73d09,0xbd4f3dea,
0x3db53d80,0xbde73d5b,0xbcaf3dfc,0xbddfbd7c,0x3de23d71,0xbd98bdce,0xbe003b49,0x3d21bdf3,0xbd153df5,0x3dacbdbe,0xbce0bdfa,0x3dfe3c7b,0xbdffbc49,0x3ddc3d84,0x3deabd4f,0x3c173dff,
0xbdb53d80,0x3df8bcf9,0x3d09bdf7,0x3db13db9,0xbc493dff,0xbd2c3df1,0x3da73dc2,0xbdfc3caf,0xbdc6bda2,0xbd98bdce,0xbdfe3c7b,0x3d4fbdea,0x3df5bd15,0x3e00bbc9,0x3d66bde5,0x3d893dd8,
0x3db53d80,0xbe003bc9,0xbd383def,0xbd66bde5,0xbdf53d15,0x3df8bcf9,0x3cafbdfc,0x3d9d3dca,0x3de2bd71,0xbde73d5b,0x3b493e00,0xbdc2bda7,0xbdc63da2,0x3dcebd98,0xbce0bdfa,0x3ddf3d7c,
0xbdb53d80,0x3dfd3c96,0x3d66bde5,0x3caf3dfc,0xbda2bdc6,0xbdbebdac,0xbddf3d7c,0x3d4fbdea,0x3c493dff,0x3cf93df8,0x3dff3c17,0xbdd83d89,0x3d71bde2,0x3d2cbdf1,0xbdcabd9d,0x3e003b49,
0x3db53d80,0xbdf1bd2c,0xbd893dd8,0x3c7bbdfe,0x3d71bde2,0xbc963dfd,0x3def3d38,0xbdff3c17,0xbdf5bd15,0x3e00bbc9,0x3cafbdfc,0x3d093df7,0xbc493dff,0xbcf9bdf8,0xbe003b49,0x3de5bd66,
0xbdb53d80,0x3ddc3d84,0x3d9dbdca,0xbd4f3dea,0x3dff3c49,0x3de7bd5b,0xbd21bdf3,0x3d893dd8,0x3da2bdc6,0x3c96bdfd,0xbdf7bd09,0x3e003b49,0xbd15bdf5,0xbdbebdac,0xbdc23da7,0x3d93bdd1,
0x3db53d80,0xbdbebdac,0xbdb13db9,0x3da7bdc2,0x3d153df5,0xbddcbd84,0xbd893dd8,0x3d7cbddf,0x3d713de2,0xbdf1bd2c,0xbd383def,0x3d21bdf3,0x3da23dc6,0xbdfdbc96,0xbcaf3dfc,0x3c7bbdfe,
0xbdb53d80,0x3d983dce,0x3dc2bda7,0xbdd83d89,0xbdc63da2,0x3bc93e00,0x3dfebc7b,0xbe00bb49,0xbdff3c49,0xbd843ddc,0x3de53d66,0xbdd1bd93,0xbde2bd71,0xbde73d5b,0x3d7c3ddf,0xbd38bdef,
0x3db53d80,0xbd5bbde7,0xbdd13d93,0x3df7bd09,0xbde2bd71,0x3dcebd98,0xbdb9bdb1,0x3d663de5,0x3d15bdf5,0x3dbe3dac,0x3d89bdd8,0xbdca3d9d,0x3dff3c49,0xbd843ddc,0x3def3d38,0xbdc2bda7,
0xbdb53d80,0x3cf93df8,0x3ddfbd7c,0xbe00bb49,0x3c49bdff,0xbdf1bd2c,0xbc173dff,0x3d93bdd1,0x3dc63da2,0x3dcebd98,0xbdcabd9d,0x3d383def,0xbdf53d15,0x3bc93e00,0x3df3bd21,0xbdfabce0,
0x3db53d80,0xbbc9be00,0xbdea3d4f,0x3df33d21,0x3df5bd15,0x3cf93df8,0x3dd1bd93,0xbdfebc7b,0xbde23d71,0xbd5bbde7,0xbdb13db9,0x3dffbc17,0x3dc6bda2,0x3d983dce,0x3d89bdd8,0xbdf73d09,
0xbdb53d80,0xbc963dfd,0x3df3bd21,0xbdd1bd93,0x3da23dc6,0x3dacbdbe,0xbdf7bd09,0x3d383def,0xbc49bdff,0xbdf83cf9,0x3da73dc2,0x3ce0bdfa,0xbd713de2,0x3df13d2c,0xbc7bbdfe,0xbdb93db1,
0x3db53d80,0x3d2cbdf1,0xbdfa3ce0,0x3d9d3dca,0xbd713de2,0xbdfdbc96,0x3d4f3dea,0x3da7bdc2,0x3df53d15,0x3bc93e00,0x3dd1bd93,0xbddfbd7c,0x3c49bdff,0x3df8bcf9,0xbdb9bdb1,0xbd213df3,
0xbdb53d80,0xbd843ddc,0x3dfebc7b,0xbd38bdef,0xbdffbc49,0x3d5b3de7,0x3d66bde5,0xbdfabce0,0xbda23dc6,0x3dfd3c96,0xbd7cbddf,0xbdb93db1,0x3d153df5,0x3dacbdbe,0xbdffbc17,0x3caf3dfc,
0x3db53d80,0x3dacbdbe,0xbe003b49,0x3c173dff,0xbd15bdf5,0x3d84bddc,0xbdfa3ce0,0x3d093df7,0xbd71bde2,0x3d2cbdf1,0xbdea3d4f,0x3d663de5,0xbda2bdc6,0x3c96bdfd,0xbdd13d93,0x3d9d3dca,
0xbdb53d80,0xbdce3d98,0x3dff3c17,0x3ce0bdfa,0x3dc6bda2,0xbe003bc9,0x3dca3d9d,0x3db9bdb1,0x3dffbc49,0xbddcbd84,0x3d213df3,0x3dfcbcaf,0x3de23d71,0xbd5bbde7,0xbd093df7,0x3dea3d4f,
0x3db53d80,0x3de7bd5b,0xbdfcbcaf,0xbd7c3ddf,0x3de23d71,0x3d983dce,0xbb49be00,0xbdf3bd21,0xbd153df5,0xbdac3dbe,0x3dfabce0,0x3c7bbdfe,0xbdffbc49,0xbddcbd84,0x3d4f3dea,0x3dffbc17,
0xbdb53d80,0xbdf83cf9,0x3df73d09,0x3db9bdb1,0xbc493dff,0x3d2cbdf1,0xbdc23da7,0x3caf3dfc,0xbdc6bda2,0x3d983dce,0xbc7bbdfe,0xbdeabd4f,0x3df5bd15,0xbe003bc9,0x3de53d66,0x3dd8bd89,
0x3db53d80,0x3e00bbc9,0xbdefbd38,0xbde53d66,0xbdf53d15,0xbdf83cf9,0x3dfc3caf,0x3dcabd9d,0x3de2bd71,0x3de7bd5b,0xbe003b49,0xbda73dc2,0xbdc63da2,0xbdce3d98,0x3dfabce0,0x3d7cbddf,
0xbdb53d80,0xbdfdbc96,0x3de53d66,0x3dfcbcaf,0xbda2bdc6,0x3dbe3dac,0xbd7cbddf,0xbdeabd4f,0x3c493dff,0xbcf9bdf8,0xbc173dff,0x3d893dd8,0x3d71bde2,0xbd2c3df1,0x3d9dbdca,0x3b49be00,
0x3db53d80,0x3df13d2c,0xbdd8bd89,0xbdfebc7b,0x3d71bde2,0x3c96bdfd,0xbd383def,0x3c173dff,0xbdf5bd15,0xbe003bc9,0x3dfc3caf,0x3df7bd09,0xbc493dff,0x3cf93df8,0xbb49be00,0xbd66bde5,
0xbdb53d80,0xbddcbd84,0x3dca3d9d,0x3dea3d4f,0x3dff3c49,0xbde73d5b,0x3df3bd21,0x3dd8bd89,0x3da2bdc6,0xbc963dfd,0x3d09bdf7,0x3b49be00,0xbd15bdf5,0x3dbe3dac,0xbda7bdc2,0xbdd1bd93,
0x3db53d80,0x3dbe3dac,0xbdb9bdb1,0xbdc2bda7,0x3d153df5,0x3ddc3d84,0xbdd8bd89,0xbddfbd7c,0x3d713de2,0x3df13d2c,0xbdefbd38,0xbdf3bd21,0x3da23dc6,0x3dfd3c96,0xbdfcbcaf,0xbdfebc7b,
0x3f800000,0x0,0x3f800000,0x0,0x3f800000,0x0,0x3f800000,0x0,0x3f800000,0x0,0x3f800000,0x0,0x3f800000,0x0,0x3f800000,0x0,
0x3f800000,0x0,0x3f7ffb11,0xbc490e90,0x3f7fec43,0xbcc90ab0,0x3f7fd397,0xbd16c32c,0x3f7fb10f,0xbd48fb30,0x3f7f84ab,0xbd7b2b74,0x3f7f4e6d,0xbd96a905,0x3f7f0e58,0xbdafb680,
0x3f800000,0x0,0x3f7fec43,0xbcc90ab0,0x3f7fb10f,0xbd48fb30,0x3f7f4e6d,0xbd96a905,0x3f7ec46d,0xbdc8bd36,0x3f7e1324,0xbdfab273,0x3f7d3aac,0xbe164083,0x3f7c3b28,0xbe2f10a2,
0x3f800000,0x0,0x3f7fd397,0xbd16c32c,0x3f7f4e6d,0xbd96a905,0x3f7e70b0,0xbde1bc2e,0x3f7d3aac,0xbe164083,0x3f7baccd,0xbe3b6ecf,0x3f79c79d,0xbe605c13,0x3f778bc5,0xbe827dc0,
0x3f800000,0x0,0x3f7fb10f,0xbd48fb30,0x3f7ec46d,0xbdc8bd36,0x3f7d3aac,0xbe164083,0x3f7b14be,0xbe47c5c2,0x3f7853f8,0xbe78cfcc,0x3f74fa0b,0xbe94a031,0x3f710908,0xbeac7cd4,
0x3f800000,0x0,0x3f7f84ab,0xbd7b2b74,0x3f7e1324,0xbdfab273,0x3f7baccd,0xbe3b6ecf,0x3f7853f8,0xbe78cfcc,0x3f740bdd,0xbe9aa086,0x3f6ed89e,0xbeb8442a,0x3f68bf3c,0xbed53641,
0x3f800000,0x0,0x3f7f4e6d,0xbd96a905,0x3f7d3aac,0xbe164083,0x3f79c79d,0xbe605c13,0x3f74fa0b,0xbe94a031,0x3f6ed89e,0xbeb8442a,0x3f676bd8,0xbedae880,0x3f5ebe05,0xbefc5d27,
0x3f800000,0x0,0x3f7f0e58,0xbdafb680,0x3f7c3b28,0xbe2f10a2,0x3f778bc5,0xbe827dc0,0x3f710908,0xbeac7cd4,0x3f68bf3c,0xbed53641,0x3f5ebe05,0xbefc5d27,0x3f531849,0xbf10d3cd,
0x3f800000,0x0,0x3f7b14be,0xbe47c5c2,0x3f6c835e,0xbec3ef15,0x3f54db31,0xbf0e39da,0x3f3504f3,0xbf3504f3,0x3f0e39da,0xbf54db31,0x3ec3ef15,0xbf6c835e,0x3e47c5c2,0xbf7b14be,
0x3f800000,0x0,0x3f7a7302,0xbe541501,0x3f6a09a7,0xbecf7bca,0x3f4f7a1f,0xbf15f6d9,0x3f2beb4a,0xbf3daef9,0x3f00e7e4,0xbf5d2d53,0x3ea09ae5,0xbf731447,0x3de1bc2e,0xbf7e70b0,
0x3f800000,0x0,0x3f79c79d,0xbe605c13,0x3f676bd8,0xbedae880,0x3f49d112,0xbf1d7fd1,0x3f226799,0xbf45e403,0x3ee63375,0xbf64aa59,0x3e78cfcc,0xbf7853f8,0x3cc90ab0,0xbf7fec43,
0x3f800000,0x0,0x3f791298,0xbe6c9a7f,0x3f64aa59,0xbee63375,0x3f43e200,0xbf24d225,0x3f187fc0,0xbf4d9f02,0x3ec9b953,0xbf6b4b0c,0x3e2f10a2,0xbf7c3b28,0xbd7b2b74,0xbf7f84ab,
0x3f800000,0x0,0x3f7853f8,0xbe78cfcc,0x3f61c598,0xbef15aea,0x3f3daef9,0xbf2beb4a,0x3f0e39da,0xbf54db31,0x3eac7cd4,0xbf710908,0x3dc8bd36,0xbf7ec46d,0xbe164083,0xbf7d3aac,
0x3f800000,0x0,0x3f778bc5,0xbe827dc0,0x3f5ebe05,0xbefc5d27,0x3f373a23,0xbf32c8c9,0x3f039c3d,0xbf5b941a,0x3e8e9a22,0xbf75dec6,0x3cc90ab0,0xbf7fec43,0xbe6c9a7f,0xbf791298,
0x3f800000,0x0,0x3f76ba07,0xbe888e93,0x3f5b941a,0xbf039c3d,0x3f3085bb,0xbf396842,0x3ef15aea,0xbf61c598,0x3e605c13,0xbf79c79d,0xbd48fb30,0xbf7fb10f,0xbea09ae5,0xbf731447,
0x3f800000,0x0,0x3f75dec6,0xbe8e9a22,0x3f584853,0xbf08f59b,0x3f299415,0xbf3fc767,0x3edae880,0xbf676bd8,0x3e22abb6,0xbf7cbfc9,0xbdfab273,0xbf7e1324,0xbec9b953,0xbf6b4b0c,
0x3f800000,0x0,0x3f7ec46d,0xbdc8bd36,0x3f7b14be,0xbe47c5c2,0x3f74fa0b,0xbe94a031,0x3f6c835e,0xbec3ef15,0x3f61c598,0xbef15aea,0x3f54db31,0xbf0e39da,0x3f45e403,0xbf226799,
0x3f800000,0x0,0x3f6b4b0c,0xbec9b953,0x3f3085bb,0xbf396842,0x3eb263ef,0xbf6ff573,0xbd48fb30,0xbf7fb10f,0xbee0924f,0xbf660f88,0xbf41d870,0xbf273656,0xbf740bdd,0xbe9aa086,
0x3f800000,0x0,0x3f6a09a7,0xbecf7bca,0x3f2beb4a,0xbf3daef9,0x3ea09ae5,0xbf731447,0xbdc8bd36,0xbf7ec46d,0xbefc5d27,0xbf5ebe05,0xbf4d9f02,0xbf187fc0,0xbf79c79d,0xbe605c13,
0x3f800000,0x0,0x3f68bf3c,0xbed53641,0x3f273656,0xbf41d870,0x3e8e9a22,0xbf75dec6,0xbe164083,0xbf7d3aac,0xbf0b9a6b,0xbf5695e5,0xbf584853,0xbf08f59b,0xbf7dabcc,0xbe09cf86,
0x3f800000,0x0,0x3f676bd8,0xbedae880,0x3f226799,0xbf45e403,0x3e78cfcc,0xbf7853f8,0xbe47c5c2,0xbf7b14be,0xbf187fc0,0xbf4d9f02,0xbf61c598,0xbef15aea,0xbf7fb10f,0xbd48fb30,
0x3f800000,0x0,0x3f660f88,0xbee0924f,0x3f1d7fd1,0xbf49d112,0x3e541501,0xbf7a7302,0xbe78cfcc,0xbf7853f8,0xbf24d225,0xbf43e200,0xbf6a09a7,0xbecf7bca,0xbf7fd397,0x3d16c32c,
0x3f800000,0x0,0x3f64aa59,0xbee63375,0x3f187fc0,0xbf4d9f02,0x3e2f10a2,0xbf7c3b28,0xbe94a031,0xbf74fa0b,0xbf3085bb,0xbf396842,0xbf710908,0xbeac7cd4,0xbf7e1324,0x3dfab273,
0x3f800000,0x0,0x3f633c5a,0xbeebcbbb,0x3f13682a,0xbf514d3d,0x3e09cf86,0xbf7dabcc,0xbeac7cd4,0xbf710908,0xbf3b8f3b,0xbf2e3bde,0xbf76ba07,0xbe888e93,0xbf7a7302,0x3e541501,
0x3f800000,0x0,0x3f74fa0b,0xbe94a031,0x3f54db31,0xbf0e39da,0x3f226799,0xbf45e403,0x3ec3ef15,0xbf6c835e,0x3dc8bd36,0xbf7ec46d,0xbe47c5c2,0xbf7b14be,0xbef15aea,0xbf61c598,
0x3f800000,0x0,0x3f531849,0xbf10d3cd,0x3eb8442a,0xbf6ed89e,0xbe6c9a7f,0xbf791298,0xbf3daef9,0xbf2beb4a,0xbf7dabcc,0xbe09cf86,0xbf64aa59,0x3ee63375,0xbef6e0cb,0x3f604621,
0x3f800000,0x0,0x3f514d3d,0xbf13682a,0x3eac7cd4,0xbf710908,0xbe888e93,0xbf76ba07,0xbf45e403,0xbf226799,0xbf7f4e6d,0xbd96a905,0xbf5b941a,0x3f039c3d,0xbecf7bca,0x3f6a09a7,
0x3f800000,0x0,0x3f4f7a1f,0xbf15f6d9,0x3ea09ae5,0xbf731447,0xbe9aa086,0xbf740bdd,0xbf4d9f02,0xbf187fc0,0xbf7ffb11,0xbc490e90,0xbf514d3d,0x3f13682a,0xbea68f12,0x3f721352,
0x3f800000,0x0,0x3f4d9f02,0xbf187fc0,0x3e94a031,0xbf74fa0b,0xbeac7cd4,0xbf710908,0xbf54db31,0xbf0e39da,0xbf7fb10f,0x3d48fb30,0xbf45e403,0x3f226799,0xbe78cfcc,0x3f7853f8,
0x3f800000,0x0,0x3f4bbbf8,0xbf1b02c6,0x3e888e93,0xbf76ba07,0xbebe1d4a,0xbf6db293,0xbf5b941a,0xbf039c3d,0xbf7e70b0,0x3de1bc2e,0xbf396842,0x3f3085bb,0xbe22abb6,0x3f7cbfc9,
0x3f800000,0x0,0x3f49d112,0xbf1d7fd1,0x3e78cfcc,0xbf7853f8,0xbecf7bca,0xbf6a09a7,0xbf61c598,0xbef15aea,0xbf7c3b28,0x3e2f10a2,0xbf2beb4a,0x3f3daef9,0xbd96a905,0x3f7f4e6d,
0x3f800000,0x0,0x3f47de65,0xbf1ff6cb,0x3e605c13,0xbf79c79d,0xbee0924f,0xbf660f88,0xbf676bd8,0xbedae880,0xbf791298,0x3e6c9a7f,0xbf1d7fd1,0x3f49d112,0x3c490e90,0x3f7ffb11,
0x3f800000,0x0,0x3f800000,0x0,0x3f800000,0x0,0x3f800000,0x0,0x40000000,0x0,0x3f800000,0x0,0x3f800000,0x0,0x3f800000,0x0,
0x3f800000,0x0,0x3f7ffb11,0xbc490e90,0x3f7fec43,0xbcc90ab0,0x3f7fd397,0xbd16c32c,0x3fffb10f,0xbdc8fb30,0x3f7f84ab,0xbd7b2b74,0x3f7f4e6d,0xbd96a905,0x3f7f0e58,0xbdafb680,
0x3f800000,0x0,0x3f7fec43,0xbcc90ab0,0x3f7fb10f,0xbd48fb30,0x3f7f4e6d,0xbd96a905,0x3ffec46d,0xbe48bd36,0x3f7e1324,0xbdfab273,0x3f7d3aac,0xbe164083,0x3f7c3b28,0xbe2f10a2,
0x3f800000,0x0,0x3f7fd397,0xbd16c32c,0x3f7f4e6d,0xbd96a905,0x3f7e70b0,0xbde1bc2e,0x3ffd3aac,0xbe964083,0x3f7baccd,0xbe3b6ecf,0x3f79c79d,0xbe605c13,0x3f778bc5,0xbe827dc0,
0x3f800000,0x0,0x3f7fb10f,0xbd48fb30,0x3f7ec46d,0xbdc8bd36,0x3f7d3aac,0xbe164083,0x3ffb14be,0xbec7c5c2,0x3f7853f8,0xbe78cfcc,0x3f74fa0b,0xbe94a031,0x3f710908,0xbeac7cd4,
0x3f800000,0x0,0x3f7f84ab,0xbd7b2b74,0x3f7e1324,0xbdfab273,0x3f7baccd,0xbe3b6ecf,0x3ff853f8,0xbef8cfcc,0x3f740bdd,0xbe9aa086,0x3f6ed89e,0xbeb8442a,0x3f68bf3c,0xbed53641,
0x3f800000,0x0,0x3f7f4e6d,0xbd96a905,0x3f7d3aac,0xbe164083,0x3f79c79d,0xbe605c13,0x3ff4fa0b,0xbf14a031,0x3f6ed89e,0xbeb8442a,0x3f676bd8,0xbedae880,0x3f5ebe05,0xbefc5d27,
0x3f800000,0x0,0x3f7f0e58,0xbdafb680,0x3f7c3b28,0xbe2f10a2,0x3f778bc5,0xbe827dc0,0x3ff10908,0xbf2c7cd4,0x3f68bf3c,0xbed53641,0x3f5ebe05,0xbefc5d27,0x3f531849,0xbf10d3cd,
0x3f800000,0x0,0x3f7ec46d,0xbdc8bd36,0x3f7b14be,0xbe47c5c2,0x3f74fa0b,0xbe94a031,0x3fec835e,0xbf43ef15,0x3f61c598,0xbef15aea,0x3f54db31,0xbf0e39da,0x3f45e403,0xbf226799,
0x3f800000,0x0,0x3f7e70b0,0xbde1bc2e,0x3f79c79d,0xbe605c13,0x3f721352,0xbea68f12,0x3fe76bd8,0xbf5ae880,0x3f59f26a,0xbf064b82,0x3f49d112,0xbf1d7fd1,0x3f373a23,0xbf32c8c9,
0x3f800000,0x0,0x3f7e1324,0xbdfab273,0x3f7853f8,0xbe78cfcc,0x3f6ed89e,0xbeb8442a,0x3fe1c598,0xbf715aea,0x3f514d3d,0xbf13682a,0x3f3daef9,0xbf2beb4a,0x3f273656,0xbf41d870,
0x3f800000,0x0,0x3f7dabcc,0xbe09cf86,0x3f76ba07,0xbe888e93,0x3f6b4b0c,0xbec9b953,0x3fdb941a,0xbf839c3d,0x3f47de65,0xbf1ff6cb,0x3f3085bb,0xbf396842,0x3f15f6d9,0xbf4f7a1f,
0x3f800000,0x0,0x3f7d3aac,0xbe164083,0x3f74fa0b,0xbe94a031,0x3f676bd8,0xbedae880,0x3fd4db31,0xbf8e39da,0x3f3daef9,0xbf2beb4a,0x3f226799,0xbf45e403,0x3f039c3d,0xbf5b941a,
0x3f800000,0x0,0x3f7cbfc9,0xbe22abb6,0x3f731447,0xbea09ae5,0x3f633c5a,0xbeebcbbb,0x3fcd9f02,0xbf987fc0,0x3f32c8c9,0xbf373a23,0x3f13682a,0xbf514d3d,0x3ee0924f,0xbf660f88,
0x3f800000,0x0,0x3f7c3b28,0xbe2f10a2,0x3f710908,0xbeac7cd4,0x3f5ebe05,0xbefc5d27,0x3fc5e403,0xbfa26799,0x3f273656,0xbf41d870,0x3f039c3d,0xbf5b941a,0x3eb8442a,0xbf6ed89e,
0x3f800000,0x0,0x3f7baccd,0xbe3b6ecf,0x3f6ed89e,0xbeb8442a,0x3f59f26a,0xbf064b82,0x3fbdaef9,0xbfabeb4a,0x3f1b02c6,0xbf4bbbf8,0x3ee63375,0xbf64aa59,0x3e8e9a22,0xbf75dec6,
0x3f800000,0x0,0x3f7b14be,0xbe47c5c2,0x3f6c835e,0xbec3ef15,0x3f54db31,0xbf0e39da,0x3fb504f3,0xbfb504f3,0x3f0e39da,0xbf54db31,0x3ec3ef15,0xbf6c835e,0x3e47c5c2,0xbf7b14be,
0x3f800000,0x0,0x3f7a7302,0xbe541501,0x3f6a09a7,0xbecf7bca,0x3f4f7a1f,0xbf15f6d9,0x3fabeb4a,0xbfbdaef9,0x3f00e7e4,0xbf5d2d53,0x3ea09ae5,0xbf731447,0x3de1bc2e,0xbf7e70b0,
0x3f800000,0x0,0x3f79c79d,0xbe605c13,0x3f676bd8,0xbedae880,0x3f49d112,0xbf1d7fd1,0x3fa26799,0xbfc5e403,0x3ee63375,0xbf64aa59,0x3e78cfcc,0xbf7853f8,0x3cc90ab0,0xbf7fec43,
0x3f800000,0x0,0x3f791298,0xbe6c9a7f,0x3f64aa59,0xbee63375,0x3f43e200,0xbf24d225,0x3f987fc0,0xbfcd9f02,0x3ec9b953,0xbf6b4b0c,0x3e2f10a2,0xbf7c3b28,0xbd7b2b74,0xbf7f84ab,
0x3f800000,0x0,0x3f7853f8,0xbe78cfcc,0x3f61c598,0xbef15aea,0x3f3daef9,0xbf2beb4a,0x3f8e39da,0xbfd4db31,0x3eac7cd4,0xbf710908,0x3dc8bd36,0xbf7ec46d,0xbe164083,0xbf7d3aac,
0x3f800000,0x0,0x3f778bc5,0xbe827dc0,0x3f5ebe05,0xbefc5d27,0x3f373a23,0xbf32c8c9,0x3f839c3d,0xbfdb941a,0x3e8e9a22,0xbf75dec6,0x3cc90ab0,0xbf7fec43,0xbe6c9a7f,0xbf791298,
0x3f800000,0x0,0x3f76ba07,0xbe888e93,0x3f5b941a,0xbf039c3d,0x3f3085bb,0xbf396842,0x3f715aea,0xbfe1c598,0x3e605c13,0xbf79c79d,0xbd48fb30,0xbf7fb10f,0xbea09ae5,0xbf731447,
0x3f800000,0x0,0x3f75dec6,0xbe8e9a22,0x3f584853,0xbf08f59b,0x3f299415,0xbf3fc767,0x3f5ae880,0xbfe76bd8,0x3e22abb6,0xbf7cbfc9,0xbdfab273,0xbf7e1324,0xbec9b953,0xbf6b4b0c,
0x3f800000,0x0,0x3f74fa0b,0xbe94a031,0x3f54db31,0xbf0e39da,0x3f226799,0xbf45e403,0x3f43ef15,0xbfec835e,0x3dc8bd36,0xbf7ec46d,0xbe47c5c2,0xbf7b14be,0xbef15aea,0xbf61c598,
0x3f800000,0x0,0x3f740bdd,0xbe9aa086,0x3f514d3d,0xbf13682a,0x3f1b02c6,0xbf4bbbf8,0x3f2c7cd4,0xbff10908,0x3d16c32c,0xbf7fd397,0xbe888e93,0xbf76ba07,0xbf0b9a6b,0xbf5695e5,
0x3f800000,0x0,0x3f731447,0xbea09ae5,0x3f4d9f02,0xbf187fc0,0x3f13682a,0xbf514d3d,0x3f14a031,0xbff4fa0b,0xbcc90ab0,0xbf7fec43,0xbeac7cd4,0xbf710908,0xbf1d7fd1,0xbf49d112,
0x3f800000,0x0,0x3f721352,0xbea68f12,0x3f49d112,0xbf1d7fd1,0x3f0b9a6b,0xbf5695e5,0x3ef8cfcc,0xbff853f8,0xbdafb680,0xbf7f0e58,0xbecf7bca,0xbf6a09a7,0xbf2e3bde,0xbf3b8f3b,
0x3f800000,0x0,0x3f710908,0xbeac7cd4,0x3f45e403,0xbf226799,0x3f039c3d,0xbf5b941a,0x3ec7c5c2,0xbffb14be,0xbe164083,0xbf7d3aac,0xbef15aea,0xbf61c598,0xbf3daef9,0xbf2beb4a,
0x3f800000,0x0,0x3f6ff573,0xbeb263ef,0x3f41d870,0xbf273656,0x3ef6e0cb,0xbf604621,0x3e964083,0xbffd3aac,0xbe541501,0xbf7a7302,0xbf08f59b,0xbf584853,0xbf4bbbf8,0xbf1b02c6,
0x3f800000,0x0,0x3f6ed89e,0xbeb8442a,0x3f3daef9,0xbf2beb4a,0x3ee63375,0xbf64aa59,0x3e48bd36,0xbffec46d,0xbe888e93,0xbf76ba07,0xbf187fc0,0xbf4d9f02,0xbf584853,0xbf08f59b,
0x3f800000,0x0,0x3f6db293,0xbebe1d4a,0x3f396842,0xbf3085bb,0x3ed53641,0xbf68bf3c,0x3dc8fb30,0xbfffb10f,0xbea68f12,0xbf721352,0xbf273656,0xbf41d870,0xbf633c5a,0xbeebcbbb,
0x3f800000,0x0,0x3f7fffb1,0xbb490fc6,0x3f7ffec4,0xbbc90f88,0x3f7ffd39,0xbc16cb58,0x3ffffb11,0xbcc90e90,0x3f7ff84a,0xbc7b514b,0x3f7ff4e6,0xbc96c9b6,0x3f7ff0e3,0xbcafea69,
0x3f800000,0x0,0x3f7ff84a,0xbc7b514b,0x3f7fe129,0xbcfb49ba,0x3f7fba9e,0xbd3c6dd5,0x3fff84ab,0xbdfb2b74,0x3f7f3f54,0xbd9cecf9,0x3f7eea9d,0xbdbc3ac3,0x3f7e868b,0xbddb7d37,
0x3f800000,0x0,0x3f7fe705,0xbce22a7a,0x3f7f9c18,0xbd621469,0x3f7f1f49,0xbda973ba,0x3ffe70b0,0xbe61bc2e,0x3f7d906e,0xbe0cec4a,0x3f7c7eb0,0xbe28defc,0x3f7b3bab,0xbe44b0b9,
0x3f800000,0x0,0x3f7fcbe2,0xbd2351cb,0x3f7f2f9d,0xbda3308c,0x3f7e2b72,0xbdf475c0,0x3ffcbfc9,0xbea2abb6,0x3f7aed37,0xbe4ada4f,0x3f78b47b,0xbe72b651,0x3f76167a,0xbe8d17c0,
0x3f800000,0x0,0x3f7fa6e3,0xbd55880e,0x3f7e9bc9,0xbdd53db9,0x3f7cdf6c,0xbe1f917b,0x3ffa7302,0xbed41501,0x3f77583a,0xbe840270,0x3f73913f,0xbe9d9e78,0x3f6f20b0,0xbeb6ccc3,
0x3f800000,0x0,0x3f7f7808,0xbd83db0a,0x3f7de0b1,0xbe039502,0x3f7b3bab,0xbe44b0b9,0x3ff78bc5,0xbf027dc0,0x3f72d4eb,0xbea21887,0x3f6d1c1d,0xbec1071e,0x3f666771,0xbedf28a9,
0x3f800000,0x0,0x3f7f3f54,0xbd9cecf9,0x3f7cfe73,0xbe1c76de,0x3f7940c0,0xbe698bba,0x3ff40bdd,0xbf1aa086,0x3f6d67a1,0xbebf926f,0x3f655e0b,0xbee363fa,0x3f5bfb34,0xbf02ef9f,
0x3f800000,0x0,0x3f7efcc9,0xbdb5f8da,0x3f7bf531,0xbe354098,0x3f76ef5b,0xbe870ada,0x3feff573,0xbf3263ef,0x3f671599,0xbedc53c1,0x3f5c61c7,0xbf0242b1,0x3f4fefa8,0xbf1553b7,
0x3f800000,0x0,0x3f7eb069,0xbdcefdb7,0x3f7ac516,0xbe4dee60,0x3f74484b,0xbe9920fe,0x3feb4b0c,0xbf49b953,0x3f5fe4e9,0xbef840c8,0x3f5233c6,0xbf121eb0,0x3f425b89,0xbf269de3,
0x3f800000,0x0,0x3f7e5a38,0xbde7fa9a,0x3f796e4e,0xbe667c66,0x3f714c7a,0xbeab0201,0x3fe60f88,0xbf60924f,0x3f57dc7f,0xbf099f4e,0x3f46e22a,0xbf212ff9,0x3f33587a,0xbf36ad7f,
0x3f800000,0x0,0x3f7dfa38,0xbe007745,0x3f77f110,0xbe7ee6e1,0x3f6dfcf2,0xbebca7af,0x3fe04621,0xbf76e0cb,0x3f4f0417,0xbf16999f,0x3f3a7ca4,0xbf2f61a5,0x3f2302d3,0xbf456439,
0x3f800000,0x0,0x3f7d906e,0xbe0cec4a,0x3f764d97,0xbe8b9507,0x3f6a5ad9,0xbece0bea,0x3fd9f26a,0xbf864b82,0x3f456439,0xbf2302d3,0x3f2d1469,0xbf3ca003,0x3f11796b,0xbf52a649,
0x3f800000,0x0,0x3f7d1cdd,0xbe195be0,0x3f748422,0xbe97a117,0x3f666771,0xbedf28a9,0x3fd31849,0xbf90d3cd,0x3f3b0629,0xbf2ecef7,0x3f1ebc12,0xbf48d8b3,0x3efdbabb,0xbf5e5aa6,
0x3f800000,0x0,0x3f7c9f8a,0xbe25c58c,0x3f7294f8,0xbea395c5,0x3f62241a,0xbeeff7fb,0x3fcbbbf8,0xbf9b02c6,0x3f2ff3e6,0xbf39f2ac,0x3f0f8784,0xbf53fac3,0x3ed6a399,0xbf686b39,
0x3f800000,0x0,0x3f7c187a,0xbe3228d4,0x3f708066,0xbeaf713a,0x3f5d924d,0xbf003a06,0x3fc3e200,0xbfa4d225,0x3f24381a,0xbf446337,0x3eff17b2,0xbf5df6be,0x3eadf73c,0xbf70c501,
0x3f800000,0x0,0x3f7b87b2,0xbe3e853e,0x3f6e46be,0xbebb31a0,0x3f58b3a1,0xbf084b92,0x3fbb8f3b,0xbfae3bde,0x3f17de12,0xbf4e1689,0x3eddbe79,0xbf66becc,0x3e840270,0xbf77583a,
0x3f800000,0x0,0x3f7aed37,0xbe4ada4f,0x3f6be858,0xbec6d529,0x3f5389c7,0xbf102dd5,0x3fb2c8c9,0xbfb73a23,0x3f0af1b7,0xbf570348,0x3ebb31a0,0xbf6e46be,0x3e3228d4,0xbf7c187a,
0x3f800000,0x0,0x3f7a4910,0xbe57278f,0x3f696591,0xbed25a09,0x3f4e1689,0xbf17de12,0x3fa99415,0xbfbfc767,0x3efafef7,0xbf5f20db,0x3e97a117,0xbf748422,0x3db5f8da,0xbf7efcc9,
0x3f800000,0x0,0x3f799b43,0xbe636c83,0x3f66becc,0xbeddbe79,0x3f485bca,0xbf1f599f,0x3f9ff6cb,0xbfc7de65,0x3edf28a9,0xbf666771,0x3e667c66,0xbf796e4e,0x3b490fc6,0xbf7fffb1,
0x3f800000,0x0,0x3f78e3d6,0xbe6fa8b2,0x3f63f473,0xbee900b7,0x3f425b89,0xbf269de3,0x3f95f6d9,0xbfcf7a1f,0x3ec27b55,0xbf6cd007,0x3e1c76de,0xbf7cfe73,0xbda973ba,0xbf7f1f49,
0x3f800000,0x0,0x3f7822d1,0xbe7bdba4,0x3f6106f2,0xbef41f07,0x3f3c17d9,0xbf2da859,0x3f8b9a6b,0xbfd695e5,0x3ea5129f,0xbf725470,0x3da3308c,0xbf7f2f9d,0xbe2bf804,0xbf7c5d3a,
0x3f800000,0x0,0x3f77583a,0xbe840270,0x3f5df6be,0xbeff17b2,0x3f3592e7,0xbf34768f,0x3f80e7e4,0xbfdd2d53,0x3e870ada,0xbf76ef5b,0x3bc90f88,0xbf7ffec4,0xbe80f8c0,0xbf77beb7,
0x3f800000,0x0,0x3f76841b,0xbe8a11f7,0x3f5ac450,0xbf04f484,0x3f2ecef7,0xbf3b0629,0x3f6bcbbb,0xbfe33c5a,0x3e5101f1,0xbf7a9c59,0xbd8a200a,0xbf7f6ac7,0xbeab0201,0xbf714c7a,
0x3f800000,0x0,0x3f75a67b,0xbe901c2c,0x3f577026,0xbf0a48ad,0x3f27ce61,0xbf4154e1,0x3f553641,0xbfe8bf3c,0x3e1324ca,0xbf7d57de,0xbe1008b7,0xbf7d7474,0xbed3c867,0xbf6912ae,
0x3f800000,0x0,0x3f74bf62,0xbe9620d2,0x3f53fac3,0xbf0f8784,0x3f209393,0xbf476085,0x3f3e1d4a,0xbfedb293,0x3da973ba,0xbf7f1f49,0xbe5a3997,0xbf7a1e84,0xbefafef7,0xbf5f20db,
0x3f800000,0x0,0x3f73ced9,0xbe9c1faf,0x3f5064af,0xbf14b039,0x3f19210f,0xbf4d26fd,0x3f268f12,0xbff21352,0x3cafea69,0xbf7ff0e3,0xbe919ddd,0xbf756d97,0xbf102dd5,0xbf5389c7,
0x3f800000,0x0,0x3f72d4eb,0xbea21887,0x3f4cae79,0xbf19c200,0x3f11796b,0xbf52a649,0x3f0e9a22,0xbff5dec6,0xbd2351cb,0xbf7fcbe2,0xbeb554ec,0xbf6f6830,0xbf21cbfb,0xbf466354,
0x3f800000,0x0,0x3f71d19f,0xbea80b1f,0x3f48d8b3,0xbf1ebc12,0x3f099f4e,0xbf57dc7f,0x3eec9a7f,0xbff91298,0xbdcefdb7,0xbf7eb069,0xbed8106b,0xbf6816a8,0xbf3238aa,0xbf37c655,
0x3f800000,0x0,0x3f70c501,0xbeadf73c,0x3f44e3f5,0xbf239da9,0x3f019573,0xbf5cc7d1,0x3ebb6ecf,0xbffbaccd,0xbe25c58c,0xbf7c9f8a,0xbef9a02d,0xbf5f8327,0xbf4154e1,0xbf27ce61,
0x3f800000,0x0,0x3f6faf1b,0xbeb3dca5,0x3f40d0da,0xbf286605,0x3ef2bd43,0xbf61668a,0x3e89cf86,0xbffdabcc,0xbe636c83,0xbf799b43,0xbf0cead0,0xbf55b993,0xbf4f0417,0xbf16999f,
0x3f800000,0x0,0x3f6e8ff8,0xbeb9bb1e,0x3f3ca003,0xbf2d1469,0x3ee1fb6a,0xbf65b710,0x3e2fb680,0xbfff0e58,0xbe901c2c,0xbf75a67b,0xbf1c420c,0xbf4ac77f,0xbf5b2c79,0xbf044889,
0x3f800000,0x0,0x3f6d67a1,0xbebf926f,0x3f385216,0xbf31a81d,0x3ed0eb2a,0xbf69b7e4,0x3d96c32c,0xbfffd397,0xbeadf73c,0xbf70c501,0xbf2ac082,0xbf3ebc1b,0xbf65b710,0xbee1fb6a,
0x3f800000,0x0,0x3f7ffec4,0xbbc90f88,0x3f7ffb11,0xbc490e90,0x3f7ff4e6,0xbc96c9b6,0x3fffec43,0xbd490ab0,0x3f7fe129,0xbcfb49ba,0x3f7fd397,0xbd16c32c,0x3f7fc38f,0xbd2fe007,
0x3f800000,0x0,0x3f7ff4e6,0xbc96c9b6,0x3f7fd397,0xbd16c32c,0x3f7f9c18,0xbd621469,0x3fff4e6d,0xbe16a905,0x3f7eea9d,0xbdbc3ac3,0x3f7e70b0,0xbde1bc2e,0x3f7de0b1,0xbe039502,
0x3f800000,0x0,0x3f7fe129,0xbcfb49ba,0x3f7f84ab,0xbd7b2b74,0x3f7eea9d,0xbdbc3ac3,0x3ffe1324,0xbe7ab273,0x3f7cfe73,0xbe1c76de,0x3f7baccd,0xbe3b6ecf,0x3f7a1e84,0xbe5a3997,
0x3f800000,0x0,0x3f7fc38f,0xbd2fe007,0x3f7f0e58,0xbdafb680,0x3f7de0b1,0xbe039502,0x3ffc3b28,0xbeaf10a2,0x3f7a1e84,0xbe5a3997,0x3f778bc5,0xbe827dc0,0x3f748422,0xbe97a117,
0x3f800000,0x0,0x3f7f9c18,0xbd621469,0x3f7e70b0,0xbde1bc2e,0x3f7c7eb0,0xbe28defc,0x3ff9c79d,0xbee05c13,0x3f764d97,0xbe8b9507,0x3f721352,0xbea68f12,0x3f6d1c1d,0xbec1071e,
0x3f800000,0x0,0x3f7f6ac7,0xbd8a200a,0x3f7dabcc,0xbe09cf86,0x3f7ac516,0xbe4dee60,0x3ff6ba07,0xbf088e93,0x3f718f57,0xbea986c4,0x3f6b4b0c,0xbec9b953,0x3f63f473,0xbee900b7,
0x3f800000,0x0,0x3f7f2f9d,0xbda3308c,0x3f7cbfc9,0xbe22abb6,0x3f78b47b,0xbe72b651,0x3ff31447,0xbf209ae5,0x3f6be858,0xbec6d529,0x3f633c5a,0xbeebcbbb,0x3f591e6a,0xbf07a136,
0x3f800000,0x0,0x3f7eea9d,0xbdbc3ac3,0x3f7baccd,0xbe3b6ecf,0x3f764d97,0xbe8b9507,0x3feed89e,0xbf38442a,0x3f655e0b,0xbee363fa,0x3f59f26a,0xbf064b82,0x3f4cae79,0xbf19c200,
0x3f800000,0x0,0x3f7e9bc9,0xbdd53db9,0x3f7a7302,0xbe541501,0x3f73913f,0xbe9d9e78,0x3fea09a7,0xbf4f7bca,0x3f5df6be,0xbeff17b2,0x3f4f7a1f,0xbf15f6d9,0x3f3ebc1b,0xbf2ac082,
0x3f800000,0x0,0x3f7e4323,0xbdee3876,0x3f791298,0xbe6c9a7f,0x3f708066,0xbeaf713a,0x3fe4aa59,0xbf663375,0x3f55b993,0xbf0cead0,0x3f43e200,0xbf24d225,0x3f2f61a5,0xbf3a7ca4,
0x3f800000,0x0,0x3f7de0b1,0xbe039502,0x3f778bc5,0xbe827dc0,0x3f6d1c1d,0xbec1071e,0x3fdebe05,0xbf7c5d27,0x3f4cae79,0xbf19c200,0x3f373a23,0xbf32c8c9,0x3f1ebc12,0xbf48d8b3,
0x3f800000,0x0,0x3f7d7474,0xbe1008b7,0x3f75dec6,0xbe8e9a22,0x3f696591,0xbed25a09,0x3fd84853,0xbf88f59b,0x3f42de29,0xbf26050a,0x3f299415,0xbf3fc767,0x3f0cead0,0xbf55b993,
0x3f800000,0x0,0x3f7cfe73,0xbe1c76de,0x3f740bdd,0xbe9aa086,0x3f655e0b,0xbee363fa,0x3fd14d3d,0xbf93682a,0x3f385216,0xbf31a81d,0x3f1b02c6,0xbf4bbbf8,0x3ef41f07,0xbf6106f2,
0x3f800000,0x0,0x3f7c7eb0,0xbe28defc,0x3f721352,0xbea68f12,0x3f6106f2,0xbef41f07,0x3fc9d112,0xbf9d7fd1,0x3f2d1469,0xbf3ca003,0x3f0b9a6b,0xbf5695e5,0x3ecc9b8b,0xbf6aab7b,
0x3f800000,0x0,0x3f7bf531,0xbe354098,0x3f6ff573,0xbeb263ef,0x3f5c61c7,0xbf0242b1,0x3fc1d870,0xbfa73656,0x3f212ff9,0xbf46e22a,0x3ef6e0cb,0xbf604621,0x3ea395c5,0xbf7294f8,
0x3f800000,0x0,0x3f7b61fc,0xbe419b37,0x3f6db293,0xbebe1d4a,0x3f577026,0xbf0a48ad,0x3fb96842,0xbfb085bb,0x3f14b039,0xbf5064af,0x3ed53641,0xbf68bf3c,0x3e72b651,0xbf78b47b,
0x3f800000,0x0,0x3f7ac516,0xbe4dee60,0x3f6b4b0c,0xbec9b953,0x3f5233c6,0xbf121eb0,0x3fb085bb,0xbfb96842,0x3f07a136,0xbf591e6a,0x3eb263ef,0xbf6ff573,0x3e1c76de,0xbf7cfe73,
0x3f800000,0x0,0x3f7a1e84,0xbe5a3997,0x3f68bf3c,0xbed53641,0x3f4cae79,0xbf19c200,0x3fa73656,0xbfc1d870,0x3ef41f07,0xbf6106f2,0x3e8e9a22,0xbf75dec6,0x3d8a200a,0xbf7f6ac7,
0x3f800000,0x0,0x3f796e4e,0xbe667c66,0x3f660f88,0xbee0924f,0x3f46e22a,0xbf212ff9,0x3f9d7fd1,0xbfc9d112,0x3ed8106b,0xbf6816a8,0x3e541501,0xbf7a7302,0xbc96c9b6,0xbf7ff4e6,
0x3f800000,0x0,0x3f78b47b,0xbe72b651,0x3f633c5a,0xbeebcbbb,0x3f40d0da,0xbf286605,0x3f93682a,0xbfd14d3d,0x3ebb31a0,0xbf6e46be,0x3e09cf86,0xbf7dabcc,0xbdd53db9,0xbf7e9bc9,
0x3f800000,0x0,0x3f77f110,0xbe7ee6e1,0x3f604621,0xbef6e0cb,0x3f3a7ca4,0xbf2f61a5,0x3f88f59b,0xbfd84853,0x3e9d9e78,0xbf73913f,0x3d7b2b74,0xbf7f84ab,0xbe419b37,0xbf7b61fc,
0x3f800000,0x0,0x3f772417,0xbe8586ce,0x3f5d2d53,0xbf00e7e4,0x3f33e7bc,0xbf36206c,0x3f7c5d27,0xbfdebe05,0x3e7ee6e1,0xbf77f110,0xbc490e90,0xbf7ffb11,0xbe8b9507,0xbf764d97,
0x3f800000,0x0,0x3f764d97,0xbe8b9507,0x3f59f26a,0xbf064b82,0x3f2d1469,0xbf3ca003,0x3f663375,0xbfe4aa59,0x3e419b37,0xbf7b61fc,0xbdafb680,0xbf7f0e58,0xbeb554ec,0xbf6f6830,
0x3f800000,0x0,0x3f756d97,0xbe919ddd,0x3f5695e5,0xbf0b9a6b,0x3f26050a,0xbf42de29,0x3f4f7bca,0xbfea09a7,0x3e039502,0xbf7de0b1,0xbe22abb6,0xbf7cbfc9,0xbeddbe79,0xbf66becc,
0x3f800000,0x0,0x3f748422,0xbe97a117,0x3f531849,0xbf10d3cd,0x3f1ebc12,0xbf48d8b3,0x3f38442a,0xbfeed89e,0x3d8a200a,0xbf7f6ac7,0xbe6c9a7f,0xbf791298,0xbf0242b1,0xbf5c61c7,
0x3f800000,0x0,0x3f73913f,0xbe9d9e78,0x3f4f7a1f,0xbf15f6d9,0x3f173c07,0xbf4e8d90,0x3f209ae5,0xbff31447,0x3bc90f88,0xbf7ffec4,0xbe9aa086,0xbf740bdd,0xbf14b039,0xbf5064af,
0x3f800000,0x0,0x3f7294f8,0xbea395c5,0x3f4bbbf8,0xbf1b02c6,0x3f0f8784,0xbf53fac3,0x3f088e93,0xbff6ba07,0xbd621469,0xbf7f9c18,0xbebe1d4a,0xbf6db293,0xbf26050a,0xbf42de29,
0x3f800000,0x0,0x3f718f57,0xbea986c4,0x3f47de65,0xbf1ff6cb,0x3f07a136,0xbf591e6a,0x3ee05c13,0xbff9c79d,0xbdee3876,0xbf7e4323,0xbee0924f,0xbf660f88,0xbf36206c,0xbf33e7bc,
0x3f800000,0x0,0x3f708066,0xbeaf713a,0x3f43e200,0xbf24d225,0x3eff17b2,0xbf5df6be,0x3eaf10a2,0xbffc3b28,0xbe354098,0xbf7bf531,0xbf00e7e4,0xbf5d2d53,0xbf44e3f5,0xbf239da9,
0x3f800000,0x0,0x3f6f6830,0xbeb554ec,0x3f3fc767,0xbf299415,0x3eee9479,0xbf628210,0x3e7ab273,0xbffe1324,0xbe72b651,0xbf78b47b,0xbf10d3cd,0xbf531849,0xbf5233c6,0xbf121eb0,
0x3f800000,0x0,0x3f6e46be,0xbebb31a0,0x3f3b8f3b,0xbf2e3bde,0x3eddbe79,0xbf66becc,0x3e16a905,0xbfff4e6d,0xbe97a117,0xbf748422,0xbf1ff6cb,0xbf47de65,0xbf5df6be,0xbeff17b2,
0x3f800000,0x0,0x3f6d1c1d,0xbec1071e,0x3f373a23,0xbf32c8c9,0x3ecc9b8b,0xbf6aab7b,0x3d490ab0,0xbfffec43,0xbeb554ec,0xbf6f6830,0xbf2e3bde,0xbf3b8f3b,0xbf6816a8,0xbed8106b,
0x3f800000,0x0,0x3f7ffd39,0xbc16cb58,0x3f7ff4e6,0xbc96c9b6,0x3f7fe705,0xbce22a7a,0x3fffd397,0xbd96c32c,0x3f7fba9e,0xbd3c6dd5,0x3f7f9c18,0xbd621469,0x3f7f7808,0xbd83db0a,
0x3f800000,0x0,0x3f7ff0e3,0xbcafea69,0x3f7fc38f,0xbd2fe007,0x3f7f7808,0xbd83db0a,0x3fff0e58,0xbe2fb680,0x3f7e868b,0xbddb7d37,0x3f7de0b1,0xbe039502,0x3f7d1cdd,0xbe195be0,
0x3f800000,0x0,0x3f7fdaaf,0xbd0a342f,0x3f7f6ac7,0xbd8a200a,0x3f7eb069,0xbdcefdb7,0x3ffdabcc,0xbe89cf86,0x3f7c5d3a,0xbe2bf804,0x3f7ac516,0xbe4dee60,0x3f78e3d6,0xbe6fa8b2,
0x3f800000,0x0,0x3f7fba9e,0xbd3c6dd5,0x3f7eea9d,0xbdbc3ac3,0x3f7d906e,0xbe0cec4a,0x3ffbaccd,0xbebb6ecf,0x3f7940c0,0xbe698bba,0x3f764d97,0xbe8b9507,0x3f72d4eb,0xbea21887,
0x3f800000,0x0,0x3f7f90b1,0xbd6ea038,0x3f7e4323,0xbdee3876,0x3f7c187a,0xbe3228d4,0x3ff91298,0xbeec9a7f,0x3f75341d,0xbe931f35,0x3f708066,0xbeaf713a,0x3f6afb8c,0xbecb2aae,
0x3f800000,0x0,0x3f7f5ce9,0xbd9064b4,0x3f7d7474,0xbe1008b7,0x3f7a4910,0xbe57278f,0x3ff5dec6,0xbf0e9a22,0x3f703b37,0xbeb0eacb,0x3f696591,0xbed25a09,0x3f61668a,0xbef2bd43,
0x3f800000,0x0,0x3f7f1f49,0xbda973ba,0x3f7c7eb0,0xbe28defc,0x3f7822d1,0xbe7bdba4,0x3ff21352,0xbf268f12,0x3f6a5ad9,0xbece0bea,0x3f6106f2,0xbef41f07,0x3f5627fe,0xbf0c42c9,
0x3f800000,0x0,0x3f7ed7d4,0xbdc27c39,0x3f7b61fc,0xbe419b37,0x3f75a67b,0xbe901c2c,0x3fedb293,0xbf3e1d4a,0x3f6398ac,0xbeea6681,0x3f577026,0xbf0a48ad,0x3f495521,0xbf1e1e22,
0x3f800000,0x0,0x3f7e868b,0xbddb7d37,0x3f7a1e84,0xbe5a3997,0x3f72d4eb,0xbea21887,0x3fe8bf3c,0xbf553641,0x3f5bfb34,0xbf02ef9f,0x3f4cae79,0xbf19c200,0x3f3b0629,0xbf2ecef7,
0x3f800000,0x0,0x3f7e2b72,0xbdf475c0,0x3f78b47b,0xbe72b651,0x3f6faf1b,0xbeb3dca5,0x3fe33c5a,0xbf6bcbbb,0x3f5389c7,0xbf102dd5,0x3f40d0da,0xbf286605,0x3f2b561b,0xbf3e35c5,
0x3f800000,0x0,0x3f7dc68c,0xbe06b26e,0x3f772417,0xbe8586ce,0x3f6c3624,0xbec5625c,0x3fdd2d53,0xbf80e7e4,0x3f4a4c87,0xbf1ce11f,0x3f33e7bc,0xbf36206c,0x3f1a6293,0xbf4c3578,
0x3f800000,0x0,0x3f7d57de,0xbe1324ca,0x3f756d97,0xbe919ddd,0x3f686b39,0xbed6a399,0x3fd695e5,0xbf8b9a6b,0x3f404c5c,0xbf28fd41,0x3f26050a,0xbf42de29,0x3f084b92,0xbf58b3a1,
0x3f800000,0x0,0x3f7cdf6c,0xbe1f917b,0x3f73913f,0xbe9d9e78,0x3f644fac,0xbee79a5d,0x3fcf7a1f,0xbf95f6d9,0x3f3592e7,0xbf34768f,0x3f173c07,0xbf4e8d90,0x3eea6681,0xbf6398ac,
0x3f800000,0x0,0x3f7c5d3a,0xbe2bf804,0x3f718f57,0xbea986c4,0x3f5fe4e9,0xbef840c8,0x3fc7de65,0xbf9ff6cb,0x3f2a2a80,0xbf3f41fc,0x3f07a136,0xbf591e6a,0x3ec27b55,0xbf6cd007,
0x3f800000,0x0,0x3f7bd14d,0xbe3857ec,0x3f6f6830,0xbeb554ec,0x3f5b2c79,0xbf044889,0x3fbfc767,0xbfa99415,0x3f1e1e22,0xbf495521,0x3eee9479,0xbf628210,0x3e9920fe,0xbf74484b,
0x3f800000,0x0,0x3f7b3bab,0xbe44b0b9,0x3f6d1c1d,0xbec1071e,0x3f5627fe,0xbf0c42c9,0x3fb73a23,0xbfb2c8c9,0x3f11796b,0xbf52a649,0x3ecc9b8b,0xbf6aab7b,0x3e5d4b1a,0xbf79f35e,
0x3f800000,0x0,0x3f7a9c59,0xbe5101f1,0x3f6aab7b,0xbecc9b8b,0x3f50d937,0xbf140c5f,0x3fae3bde,0xbfbb8f3b,0x3f044889,0xbf5b2c79,0x3ea986c4,0xbf718f57,0x3e06b26e,0xbf7dc68c,
0x3f800000,0x0,0x3f79f35e,0xbe5d4b1a,0x3f6816a8,0xbed8106b,0x3f4b41fa,0xbf1ba299,0x3fa4d225,0xbfc3e200,0x3eed3063,0xbf62df7b,0x3e8586ce,0xbf772417,0x3d3c6dd5,0xbf7fba9e,
0x3f800000,0x0,0x3f7940c0,0xbe698bba,0x3f655e0b,0xbee363fa,0x3f456439,0xbf2302d3,0x3f9b02c6,0xbfcbbbf8,0x3ed0eb2a,0xbf69b7e4,0x3e419b37,0xbf7b61fc,0xbd2351cb,0xbf7fcbe2,
0x3f800000,0x0,0x3f788486,0xbe75c35a,0x3f628210,0xbeee9479,0x3f3f41fc,0xbf2a2a80,0x3f90d3cd,0xbfd31849,0x3eb3dca5,0xbf6faf1b,0x3dee3876,0xbf7e4323,0xbe007745,0xbf7dfa38,
0x3f800000,0x0,0x3f77beb7,0xbe80f8c0,0x3f5f8327,0xbef9a02d,0x3f38dd65,0xbf311722,0x3f864b82,0xbfd9f26a,0x3e9620d2,0xbf74bf62,0x3d2fe007,0xbf7fc38f,0xbe57278f,0xbf7a4910,
0x3f800000,0x0,0x3f76ef5b,0xbe870ada,0x3f5c61c7,0xbf0242b1,0x3f3238aa,0xbf37c655,0x3f76e0cb,0xbfe04621,0x3e6fa8b2,0xbf78e3d6,0xbcfb49ba,0xbf7fe129,0xbe9620d2,0xbf74bf62,
0x3f800000,0x0,0x3f76167a,0xbe8d17c0,0x3f591e6a,0xbf07a136,0x3f2b561b,0xbf3e35c5,0x3f60924f,0xbfe60f88,0x3e3228d4,0xbf7c187a,0xbdd53db9,0xbf7e9bc9,0xbebf926f,0xbf6d67a1,
0x3f800000,0x0,0x3f75341d,0xbe931f35,0x3f55b993,0xbf0cead0,0x3f24381a,0xbf446337,0x3f49b953,0xbfeb4b0c,0x3de7fa9a,0xbf7e5a38,0xbe354098,0xbf7bf531,0xbee79a5d,0xbf644fac,
0x3f800000,0x0,0x3f74484b,0xbe9920fe,0x3f5233c6,0xbf121eb0,0x3f1ce11f,0xbf4a4c87,0x3f3263ef,0xbfeff573,0x3d55880e,0xbf7fa6e3,0xbe7ee6e1,0xbf77f110,0xbf06f686,0xbf5988ad,
0x3f800000,0x0,0x3f73530e,0xbe9f1cdf,0x3f4e8d90,0xbf173c07,0x3f1553b7,0xbf4fefa8,0x3f1aa086,0xbff40bdd,0xbc16cb58,0xbf7ffd39,0xbea395c5,0xbf7294f8,0xbf19210f,0xbf4d26fd,
0x3f800000,0x0,0x3f725470,0xbea5129f,0x3f4ac77f,0xbf1c420c,0x3f0d9281,0xbf554aa4,0x3f027dc0,0xbff78bc5,0xbd9064b4,0xbf7f5ce9,0xbec6d529,0xbf6be858,0xbf2a2a80,0xbf3f41fc,
0x3f800000,0x0,0x3f714c7a,0xbeab0201,0x3f46e22a,0xbf212ff9,0x3f05a02c,0xbf5a5ba0,0x3ed41501,0xbffa7302,0xbe06b26e,0xbf7dc68c,0xbee900b7,0xbf63f473,0xbf39f2ac,0xbf2ff3e6,
0x3f800000,0x0,0x3f703b37,0xbeb0eacb,0x3f42de29,0xbf26050a,0x3efafef7,0xbf5f20db,0x3ea2abb6,0xbffcbfc9,0xbe44b0b9,0xbf7b3bab,0xbf04f484,0xbf5ac450,0xbf485bca,0xbf1f599f,
0x3f800000,0x0,0x3f6f20b0,0xbeb6ccc3,0x3f3ebc1b,0xbf2ac082,0x3eea6681,0xbf6398ac,0x3e61bc2e,0xbffe70b0,0xbe80f8c0,0xbf77beb7,0xbf14b039,0xbf5064af,0xbf554aa4,0xbf0d9281,
0x3f800000,0x0,0x3f6dfcf2,0xbebca7af,0x3f3a7ca4,0xbf2f61a5,0x3ed97cb9,0xbf67c187,0x3dfb2b74,0xbfff84ab,0xbe9f1cdf,0xbf73530e,0xbf239da9,0xbf44e3f5,0xbf60a6cf,0xbef58035,
0x3f800000,0x0,0x3f6cd007,0xbec27b55,0x3f36206c,0xbf33e7bc,0x3ec8477c,0xbf6b99fb,0x3cc90e90,0xbffffb11,0xbebca7af,0xbf6dfcf2,0xbf31a81d,0xbf385216,0xbf6a5ad9,0xbece0bea,
0x3f800000,0x0,0x0,0x0,0x0,0x0,0x0,0x0,0x0,0x0,0x0,0x0,0x0,0x0,0x0,0x0,
0x0,0x0,0x0,0x0,0x0,0x0,0x0,0x0,0x0,0x0,0x0,0x0,0x0,0x0,0x0,0x0,
0x0,0x0,0x3e000000,0xbf20dff7,0x3ed0c429,0x0,0x3e000000,0x3e61f78b,0x3e0a8bd4,0x0,0x3e000000,0x3d5413cd,0x3d5df9ad,0x0,0x3e000000,0x3cf043ab,
0x0,0x0,0x3e000000,0x3ccbafaf,0xbd5df9ad,0x0,0x3e000000,0x3cf043ab,0xbe0a8bd4,0x0,0x3e000000,0x3d5413cd,0xbed0c429,0x0,0x3e000000,0x3e61f78b,
0x0,0x0,0x0,0x0,0x3f000000,0x0,0x0,0x3f000000,0x0,0x0,0x0,0x0,0x0,0x0,0x0,0x0,
0x0,0x0,0x0,0x0,0x0,0x0,0x0,0x0,0x0,0x0,0x0,0x0,0x3f000000,0x0,0x0,0xbf000000,
0x0,0x0,0x3e000000,0xbe3f90c7,0xbe8b7e3f,0x0,0x3e000000,0xbeb641af,0x3ea73d75,0x0,0x3e000000,0x3e9a827a,0x3da61ad1,0x0,0x3e000000,0x3dd906bd,
0x0,0x0,0x3e000000,0x3dab0dc1,0xbda61ad1,0x0,0x3e000000,0x3dd906bd,0xbea73d75,0x0,0x3e000000,0x3e9a827a,0x3e8b7e3f,0x0,0x3e000000,0xbeb641af,
0x0,0x0,0x0,0x0,0x0,0x0,0x0,0x0,0x3f000000,0x0,0x0,0x3f000000,0x0,0x0,0x0,0x0,
0x0,0x0,0x0,0x0,0x0,0x0,0x0,0x0,0x3f000000,0x0,0x0,0xbf000000,0x0,0x0,0x0,0x0,
0x0,0x0,0x3e000000,0xbdab0dc1,0xbda61ad1,0x0,0x3e000000,0xbdd906bd,0xbea73d75,0x0,0x3e000000,0xbe9a827a,0x3e8b7e3f,0x0,0x3e000000,0x3eb641af,
0x0,0x0,0x3e000000,0x3e3f90c7,0xbe8b7e3f,0x0,0x3e000000,0x3eb641af,0x3ea73d75,0x0,0x3e000000,0xbe9a827a,0x3da61ad1,0x0,0x3e000000,0xbdd906bd,
0x0,0x0,0x0,0x0,0x0,0x0,0x0,0x0,0x0,0x0,0x0,0x0,0x3f000000,0x0,0x0,0x3f000000,
0x0,0x0,0x0,0x0,0x3f000000,0x0,0x0,0xbf000000,0x0,0x0,0x0,0x0,0x0,0x0,0x0,0x0,
0x0,0x0,0x3e000000,0xbccbafaf,0xbd5df9ad,0x0,0x3e000000,0xbcf043ab,0xbe0a8bd4,0x0,0x3e000000,0xbd5413cd,0xbed0c429,0x0,0x3e000000,0xbe61f78b,
0x0,0x0,0x3e000000,0x3f20dff7,0x3ed0c429,0x0,0x3e000000,0xbe61f78b,0x3e0a8bd4,0x0,0x3e000000,0xbd5413cd,0x3d5df9ad,0x0,0x3e000000,0xbcf043ab,
};

struct Params {
    const __nv_bfloat16 *wr, *wi, *lre, *lim, *ldt, *dsk;
    float* out;
};

struct cf { float x, y; };
#define YIELD() asm volatile("pmevent 1;")
#define YS 14
#define YIELD_S1() do { if (YS & 1) YIELD(); } while (0)
#define YIELD_S2() do { if (YS & 2) YIELD(); } while (0)
#define YIELD_S3() do { if (YS & 4) YIELD(); } while (0)
__device__ __forceinline__ uint32_t smem_u32(const void* p) { return (uint32_t)__cvta_generic_to_shared(p); }
__device__ __forceinline__ void mbar_init(uint32_t a, uint32_t c) { asm volatile("mbarrier.init.shared::cta.b64 [%0], %1;" ::"r"(a), "r"(c) : "memory"); }
__device__ __forceinline__ void mbar_expect_tx(uint32_t a, uint32_t b) { asm volatile("mbarrier.arrive.expect_tx.shared::cta.b64 _, [%0], %1;" ::"r"(a), "r"(b) : "memory"); }
__device__ __forceinline__ void mbar_arrive(uint32_t a) { asm volatile("mbarrier.arrive.shared::cta.b64 _, [%0];" ::"r"(a) : "memory"); }
__device__ __forceinline__ void warp_arrive(uint32_t a) {
    __syncwarp();
    asm volatile("{.reg .pred p; elect.sync _|p, 0xffffffff; @p mbarrier.arrive.shared::cta.b64 _, [%0];}" ::"r"(a) : "memory");
}
__device__ __forceinline__ uint32_t mbar_try(uint32_t a, uint32_t ph) {
    uint32_t ok;
    asm volatile("{.reg .pred p; mbarrier.try_wait.parity.shared::cta.b64 p, [%1], %2; selp.u32 %0, 1, 0, p;}" : "=r"(ok) : "r"(a), "r"(ph) : "memory");
    return ok;
}
__device__ __forceinline__ void mbar_wait(uint32_t a, uint32_t ph) {
    uint32_t ok, n = 0;
    do { ok = mbar_try(a, ph); } while (!ok && ++n < SPIN_LIMIT);
}
__device__ __forceinline__ void mbar_wait_fast(uint32_t a, uint32_t ph) { if (!mbar_try(a, ph)) mbar_wait(a, ph); }
__device__ __forceinline__ unsigned ld_rlx(const unsigned* p) { unsigned v; asm volatile("ld.relaxed.gpu.global.u32 %0, [%1];" : "=r"(v) : "l"(p) : "memory"); return v; }
__device__ __forceinline__ void wait_cnt(const unsigned* p, unsigned target) {
    unsigned n = 0;
    while ((int)(ld_rlx(p) - target) < 0 && ++n < SPIN_LIMIT) __nanosleep(20);
}
__device__ __forceinline__ void red_hint(unsigned* p) { asm volatile("red.relaxed.gpu.global.add.u32 [%0], 1;" ::"l"(p) : "memory"); }
__device__ __forceinline__ void fence_async_sm() { asm volatile("fence.proxy.async.shared::cta;" ::: "memory"); }
#define bar_sync(id, n) asm volatile("bar.sync %0, %1;" ::"n"(id), "n"(n) : "memory")
#define bar_arrive(id, n) asm volatile("bar.arrive %0, %1;" ::"n"(id), "n"(n) : "memory")
__device__ __forceinline__ bool elect_one() {
    uint32_t r;
    asm volatile("{.reg .pred p; elect.sync _|p, 0xffffffff; selp.u32 %0, 1, 0, p;}" : "=r"(r));
    return r != 0;
}

__device__ __forceinline__ void tma2d(uint32_t dst, const CUtensorMap* m, int c0, int c1, uint32_t bar) {
    asm volatile("cp.async.bulk.tensor.2d.shared::cluster.global.mbarrier::complete_tx::bytes [%0], [%1, {%3,%4}], [%2];" ::"r"(dst), "l"(m), "r"(bar), "r"(c0), "r"(c1) : "memory");
}
__device__ __forceinline__ void tma3d(uint32_t dst, const CUtensorMap* m, int c0, int c1, int c2, uint32_t bar) {
    asm volatile("cp.async.bulk.tensor.3d.shared::cluster.global.mbarrier::complete_tx::bytes [%0], [%1, {%3,%4,%5}], [%2];" ::"r"(dst), "l"(m), "r"(bar), "r"(c0), "r"(c1), "r"(c2) : "memory");
}
__device__ __forceinline__ void tma4d_mc(uint32_t dst, const CUtensorMap* m, int c0, int c1, int c2, int c3, uint32_t bar) {
    asm volatile("cp.async.bulk.tensor.4d.shared::cluster.global.mbarrier::complete_tx::bytes.multicast::cluster [%0], [%1, {%3,%4,%5,%6}], [%2], %7;" ::"r"(dst), "l"(m), "r"(bar), "r"(c0), "r"(c1), "r"(c2), "r"(c3), "h"((uint16_t)3) : "memory");
}
__device__ __forceinline__ void tma4d(uint32_t dst, const CUtensorMap* m, int c0, int c1, int c2, int c3, uint32_t bar) {
    asm volatile("cp.async.bulk.tensor.4d.shared::cluster.global.mbarrier::complete_tx::bytes [%0], [%1, {%3,%4,%5,%6}], [%2];" ::"r"(dst), "l"(m), "r"(bar), "r"(c0), "r"(c1), "r"(c2), "r"(c3) : "memory");
}
__device__ __forceinline__ void tma2d_st(const CUtensorMap* m, int c0, int c1, uint32_t src) {
    asm volatile("cp.async.bulk.tensor.2d.global.shared::cta.bulk_group [%0, {%2,%3}], [%1];" ::"l"(m), "r"(src), "r"(c0), "r"(c1) : "memory");
}
__device__ __forceinline__ void tma5d(uint32_t dst, const CUtensorMap* m, int c0, int c1, int c2, int c3, int c4, uint32_t bar) {
    asm volatile("cp.async.bulk.tensor.5d.shared::cluster.global.mbarrier::complete_tx::bytes [%0], [%1, {%3,%4,%5,%6,%7}], [%2];" ::"r"(dst), "l"(m), "r"(bar), "r"(c0), "r"(c1), "r"(c2), "r"(c3), "r"(c4) : "memory");
}
__device__ __forceinline__ void bulk_ld(uint32_t dst, const void* src, uint32_t n, uint32_t bar) {
    asm volatile("cp.async.bulk.shared::cluster.global.mbarrier::complete_tx::bytes [%0], [%1], %2, [%3];" ::"r"(dst), "l"(src), "r"(n), "r"(bar) : "memory");
}
__device__ __forceinline__ void bulk_st(void* dst, uint32_t src, uint32_t n) {
    asm volatile("cp.async.bulk.global.shared::cta.bulk_group [%0], [%1], %2;" ::"l"(dst), "r"(src), "r"(n) : "memory");
}
__device__ __forceinline__ void bulk_commit() { asm volatile("cp.async.bulk.commit_group;" ::: "memory"); }
__device__ __forceinline__ void bulk_wait_read() { asm volatile("cp.async.bulk.wait_group.read 0;" ::: "memory"); }
__device__ __forceinline__ void bulk_wait_all() { asm volatile("cp.async.bulk.wait_group 0;" ::: "memory"); }
__device__ __forceinline__ void stsm4(uint32_t a, uint32_t r0, uint32_t r1, uint32_t r2, uint32_t r3) {
    asm volatile("stmatrix.sync.aligned.m8n8.x4.shared.b16 [%0], {%1,%2,%3,%4};" ::"r"(a), "r"(r0), "r"(r1), "r"(r2), "r"(r3) : "memory");
}
__device__ __forceinline__ void sts128(uint32_t a, uint32_t r0, uint32_t r1, uint32_t r2, uint32_t r3) {
    asm volatile("st.shared.v4.b32 [%0], {%1,%2,%3,%4};" ::"r"(a), "r"(r0), "r"(r1), "r"(r2), "r"(r3) : "memory");
}
__device__ __forceinline__ void lds128f(uint32_t a, float& x, float& y, float& z, float& u) { asm volatile("ld.shared.v4.f32 {%0,%1,%2,%3}, [%4];" : "=f"(x), "=f"(y), "=f"(z), "=f"(u) : "r"(a) : "memory"); }
__device__ __forceinline__ cf lds_cf(uint32_t a) { cf v; asm volatile("ld.shared.v2.f32 {%0,%1}, [%2];" : "=f"(v.x), "=f"(v.y) : "r"(a) : "memory"); return v; }
__device__ __forceinline__ void stg128(const void* a, uint32_t r0, uint32_t r1, uint32_t r2, uint32_t r3) {
    asm volatile("st.global.v4.b32 [%0], {%1,%2,%3,%4};" ::"l"(a), "r"(r0), "r"(r1), "r"(r2), "r"(r3) : "memory");
}
__device__ __forceinline__ int fresh_lane() { int v; asm volatile("mov.u32 %0, %%laneid;" : "=r"(v)); return v; }
__device__ __forceinline__ uint32_t opaque32(uint32_t v) { asm volatile("" : "+r"(v)); return v; }
__device__ __forceinline__ const uint8_t* padd(const void* base, uint32_t off) {
    uint64_t r;
    asm("{.reg .u32 l, h; mov.b64 {l, h}, %1; add.cc.u32 l, l, %2; addc.u32 h, h, 0; mov.b64 %0, {l, h};}" : "=l"(r) : "l"(base), "r"(off));
    return (const uint8_t*)r;
}
template <int N, int STRIDE> __device__ __forceinline__ void ldtab(uint32_t (&v)[4 * N], uint32_t off) {
    const uint8_t* a = padd(g_tab, off);
#pragma unroll
    for (int i = 0; i < N; i++)
        asm volatile("ld.global.nc.v4.b32 {%0,%1,%2,%3}, [%4];" : "=r"(v[4 * i]), "=r"(v[4 * i + 1]), "=r"(v[4 * i + 2]), "=r"(v[4 * i + 3]) : "l"(a + i * STRIDE));
}
template <int STRIDE> __device__ __forceinline__ void ldtab_cf(cf (&t)[8], uint32_t off) {
    uint32_t v[16];
    ldtab<4, STRIDE>(v, off);
#pragma unroll
    for (int i = 0; i < 8; i++) t[i] = {__uint_as_float(v[2 * i]), __uint_as_float(v[2 * i + 1])};
}
__device__ __forceinline__ uint32_t lds16(uint32_t a) { uint32_t v; asm volatile("ld.shared.u16 %0, [%1];" : "=r"(v) : "r"(a)); return v; }
__device__ __forceinline__ unsigned get_epoch(uint32_t bars) {
    mbar_wait(bars + B_EP, 0);
    unsigned e;
    asm volatile("ld.shared.u32 %0, [%1];" : "=r"(e) : "r"(bars + B_EPOCH) : "memory");
    return e;
}
__device__ __forceinline__ void sts64(uint32_t a, uint32_t x, uint32_t y) { asm volatile("st.shared.v2.b32 [%0], {%1,%2};" ::"r"(a), "r"(x), "r"(y) : "memory"); }
__device__ __forceinline__ uint32_t pk(float lo, float hi) { uint32_t r; asm("cvt.rn.bf16x2.f32 %0, %1, %2;" : "=r"(r) : "f"(hi), "f"(lo)); return r; }
__device__ __forceinline__ float bf2f(unsigned short v) { return __uint_as_float((uint32_t)v << 16); }

__device__ __forceinline__ uint64_t mkdesc(uint32_t addr, uint32_t lbo, uint32_t sbo, uint32_t swz) {
    return (uint64_t)((addr & 0x3FFFF) >> 4) | ((uint64_t)(lbo >> 4) << 16) | ((uint64_t)(sbo >> 4) << 32) | ((uint64_t)swz << 62);
}
__device__ __forceinline__ uint64_t opaque(uint64_t v) { asm volatile("" : "+l"(v)); return v; }
__device__ __forceinline__ void wg_fence() { asm volatile("wgmma.fence.sync.aligned;" ::: "memory"); }
__device__ __forceinline__ void wg_commit() { asm volatile("wgmma.commit_group.sync.aligned;" ::: "memory"); }
template <int N> __device__ __forceinline__ void wg_wait() { asm volatile("wgmma.wait_group.sync.aligned %0;" ::"n"(N) : "memory"); }
template <int N> __device__ __forceinline__ void pin(float (&d)[N]) {
#pragma unroll
    for (int i = 0; i < N; i++) asm volatile("" : "+f"(d[i])::"memory");
}
template <int N> __device__ __forceinline__ void pinu(uint32_t (&d)[N]) {
#pragma unroll
    for (int i = 0; i < N; i++) asm volatile("" : "+r"(d[i])::"memory");
}

#define R8(d, o) "+f"(d[o]), "+f"(d[o + 1]), "+f"(d[o + 2]), "+f"(d[o + 3]), "+f"(d[o + 4]), "+f"(d[o + 5]), "+f"(d[o + 6]), "+f"(d[o + 7])
#define L8 "%0,%1,%2,%3,%4,%5,%6,%7"
#define L32 L8 ",%8,%9,%10,%11,%12,%13,%14,%15,%16,%17,%18,%19,%20,%21,%22,%23,%24,%25,%26,%27,%28,%29,%30,%31"
#define L56 L32 ",%32,%33,%34,%35,%36,%37,%38,%39,%40,%41,%42,%43,%44,%45,%46,%47,%48,%49,%50,%51,%52,%53,%54,%55"
#define L64 L56 ",%56,%57,%58,%59,%60,%61,%62,%63"

template <int O, int TA, int TB, int N> __device__ __forceinline__ void mma128_ss(float (&d)[N], uint64_t da, uint64_t db, int sc) {
    asm volatile("{.reg .pred p; setp.ne.b32 p, %66, 0;\n"
                 "wgmma.mma_async.sync.aligned.m64n128k16.f32.bf16.bf16 {" L64 "}, %64, %65, p, 1, 1, %67, %68;}"
                 : R8(d, O), R8(d, O + 8), R8(d, O + 16), R8(d, O + 24), R8(d, O + 32), R8(d, O + 40), R8(d, O + 48), R8(d, O + 56)
                 : "l"(da), "l"(db), "r"(sc), "n"(TA), "n"(TB));
}
template <int O, int TB> __device__ __forceinline__ void mma128_rs(float (&d)[128], uint32_t a0, uint32_t a1, uint32_t a2, uint32_t a3, uint64_t db, int sc) {
    asm volatile("{.reg .pred p; setp.ne.b32 p, %69, 0;\n"
                 "wgmma.mma_async.sync.aligned.m64n128k16.f32.bf16.bf16 {" L64 "}, {%64,%65,%66,%67}, %68, p, 1, 1, %70;}"
                 : R8(d, O), R8(d, O + 8), R8(d, O + 16), R8(d, O + 24), R8(d, O + 32), R8(d, O + 40), R8(d, O + 48), R8(d, O + 56)
                 : "r"(a0), "r"(a1), "r"(a2), "r"(a3), "l"(db), "r"(sc), "n"(TB));
}
template <int TB> __device__ __forceinline__ void mma64_rs(float (&d)[32], uint32_t a0, uint32_t a1, uint32_t a2, uint32_t a3, uint64_t db, int sc) {
    asm volatile("{.reg .pred p; setp.ne.b32 p, %37, 0;\n"
                 "wgmma.mma_async.sync.aligned.m64n64k16.f32.bf16.bf16 {" L32 "}, {%32,%33,%34,%35}, %36, p, 1, 1, %38;}"
                 : R8(d, 0), R8(d, 8), R8(d, 16), R8(d, 24)
                 : "r"(a0), "r"(a1), "r"(a2), "r"(a3), "l"(db), "r"(sc), "n"(TB));
}
__device__ __forceinline__ void mma112_ss(float (&d)[64], uint64_t da, uint64_t db, int sc) {
    asm volatile("{.reg .pred p; setp.ne.b32 p, %58, 0;\n"
                 "wgmma.mma_async.sync.aligned.m64n112k16.f32.bf16.bf16 {" L56 "}, %56, %57, p, 1, 1, 0, 1;}"
                 : R8(d, 8), R8(d, 16), R8(d, 24), R8(d, 32), R8(d, 40), R8(d, 48), R8(d, 56)
                 : "l"(da), "l"(db), "r"(sc));
}
__device__ __forceinline__ void mma16_rs(float (&d)[64], uint32_t a0, uint32_t a1, uint32_t a2, uint32_t a3, uint64_t db, int sc) {
    asm volatile("{.reg .pred p; setp.ne.b32 p, %13, 0;\n"
                 "wgmma.mma_async.sync.aligned.m64n16k16.f32.bf16.bf16 {" L8 "}, {%8,%9,%10,%11}, %12, p, 1, 1, 1;}"
                 : R8(d, 0)
                 : "r"(a0), "r"(a1), "r"(a2), "r"(a3), "l"(db), "r"(sc));
}

__device__ __forceinline__ cf cmul(cf a, cf b) { return {fmaf(a.x, b.x, -a.y * b.y), fmaf(a.x, b.y, a.y * b.x)}; }
__device__ __forceinline__ cf cmulc(cf a, cf b) { return {fmaf(a.x, b.x, a.y * b.y), fmaf(a.y, b.x, -a.x * b.y)}; }
__device__ __forceinline__ cf cfma(cf a, cf b, cf c) { return {fmaf(a.x, b.x, fmaf(-a.y, b.y, c.x)), fmaf(a.x, b.y, fmaf(a.y, b.x, c.y))}; }
__device__ __forceinline__ cf csq(cf a) { return {fmaf(a.x, a.x, -a.y * a.y), (a.x * a.y) * 2.f}; }
__device__ __forceinline__ cf csel(int c, cf a, cf b) {
    cf r;
    asm("{.reg .pred p; setp.ne.s32 p, %2, 0; selp.f32 %0, %3, %5, p; selp.f32 %1, %4, %6, p;}" : "=f"(r.x), "=f"(r.y) : "r"(c), "f"(a.x), "f"(a.y), "f"(b.x), "f"(b.y));
    return r;
}
__device__ __forceinline__ cf cadd(cf a, cf b) { return {a.x + b.x, a.y + b.y}; }
__device__ __forceinline__ cf csub(cf a, cf b) { return {a.x - b.x, a.y - b.y}; }
__device__ __forceinline__ cf twice_minus(cf a, cf s) { return {fmaf(2.f, a.x, -s.x), fmaf(2.f, a.y, -s.y)}; }
__device__ __forceinline__ cf twid(int m, int M) {
    int r = ((m + M / 2) & (M - 1)) - M / 2;
    float s, c;
    __sincosf((float)r * (-6.283185307179586f / (float)M), &s, &c);
    return {c, s};
}
struct c2 { cf a, b; };
#define YP1 3
#define YP3 3
template <int Y> __device__ __forceinline__ void fin(c2& u) { if (Y & 1) asm volatile("pmevent 1;" : "+f"(u.a.x), "+f"(u.a.y), "+f"(u.b.x), "+f"(u.b.y)); }
template <int Y> __device__ __forceinline__ void fin(c2& u, c2& v) {
    if (Y & 2) asm volatile("pmevent 1;" : "+f"(u.a.x), "+f"(u.a.y), "+f"(u.b.x), "+f"(u.b.y), "+f"(v.a.x), "+f"(v.a.y), "+f"(v.b.x), "+f"(v.b.y));
}
__device__ __forceinline__ c2 mul2(c2 u, cf t) { return {cmul(u.a, t), cmul(u.b, t)}; }
__device__ __forceinline__ c2 mul2(c2 u, c2 t) { return {cmul(u.a, t.a), cmul(u.b, t.b)}; }
__device__ __forceinline__ c2 fma2(c2 u, cf t, c2 c) { return {cfma(u.a, t, c.a), cfma(u.b, t, c.b)}; }
__device__ __forceinline__ c2 fma2(c2 u, c2 t, c2 c) { return {cfma(u.a, t.a, c.a), cfma(u.b, t.b, c.b)}; }
__device__ __forceinline__ c2 twm2(c2 u, c2 s) { return {twice_minus(u.a, s.a), twice_minus(u.b, s.b)}; }
template <int Y> __device__ __forceinline__ void bfly(c2& u, c2& v) { const c2 t = u; u = {cadd(t.a, v.a), cadd(t.b, v.b)}; v = {csub(t.a, v.a), csub(t.b, v.b)}; fin<Y>(u, v); }
template <int Y> __device__ __forceinline__ void bfly_mi(c2& u, c2& v) {
    const c2 t = u, z = v;
    u = {{t.a.x + z.a.y, t.a.y - z.a.x}, {t.b.x + z.b.y, t.b.y - z.b.x}};
    v = {{t.a.x - z.a.y, t.a.y + z.a.x}, {t.b.x - z.b.y, t.b.y + z.b.x}};
    fin<Y>(u, v);
}
template <int Y> __device__ __forceinline__ void bfly_s(c2& u, c2& v) {
    const float s = 0.70710678118654752f;
    const c2 t = u, z = v;
    u = {{fmaf(s, z.a.x, t.a.x), fmaf(s, z.a.y, t.a.y)}, {fmaf(s, z.b.x, t.b.x), fmaf(s, z.b.y, t.b.y)}};
    v = {{fmaf(-s, z.a.x, t.a.x), fmaf(-s, z.a.y, t.a.y)}, {fmaf(-s, z.b.x, t.b.x), fmaf(-s, z.b.y, t.b.y)}};
    fin<Y>(u, v);
}
template <int Y, class T> __device__ __forceinline__ void bfly_tw(c2& u0, c2& v0, T t0, c2& u1, c2& v1, T t1) {
    v0 = fma2(v0, t0, u0); fin<Y>(v0);
    v1 = fma2(v1, t1, u1); fin<Y>(v1);
    const c2 a = twm2(u0, v0), b = twm2(u1, v1);
    u0 = v0; u1 = v1; v0 = a; v1 = b;
    fin<Y>(v0, v1);
}
template <bool TW, int Y> __device__ __forceinline__ void dft8(c2 (&v)[8], const cf (&tw)[8]) {
    if (TW) {
#pragma unroll
        for (int n = 1; n < 4; n++) { v[n] = mul2(v[n], tw[n]); fin<Y>(v[n]); }
        bfly_tw<Y>(v[0], v[4], tw[4], v[2], v[6], tw[6]);
        bfly_tw<Y>(v[1], v[5], tw[5], v[3], v[7], tw[7]);
    } else {
#pragma unroll
        for (int n = 0; n < 4; n++) bfly<Y>(v[n], v[n + 4]);
    }
    bfly<Y>(v[0], v[2]); bfly_mi<Y>(v[4], v[6]);
    bfly<Y>(v[1], v[3]); bfly_mi<Y>(v[5], v[7]);
    v[5] = {{v[5].a.x + v[5].a.y, v[5].a.y - v[5].a.x}, {v[5].b.x + v[5].b.y, v[5].b.y - v[5].b.x}};
    v[7] = {{v[7].a.y - v[7].a.x, -v[7].a.x - v[7].a.y}, {v[7].b.y - v[7].b.x, -v[7].b.x - v[7].b.y}};
    fin<Y>(v[5], v[7]);
    bfly<Y>(v[0], v[1]); bfly_s<Y>(v[4], v[5]); bfly_mi<Y>(v[2], v[3]); bfly_s<Y>(v[6], v[7]);
    const c2 t1 = v[1], t3 = v[3];
    v[1] = v[4]; v[4] = t1; v[3] = v[6]; v[6] = t3;
}

__device__ __forceinline__ void gather(uint64_t (&fv)[4], const uint8_t* a, int n) {
    asm volatile("{.reg .pred p0, p1, p2, p3;\n"
                 "setp.ge.s32 p0, %5, 0; setp.ge.s32 p1, %5, 4; setp.ge.s32 p2, %5, 8; setp.ge.s32 p3, %5, 12;\n"
                 "@p0 ld.relaxed.gpu.global.b64 %0, [%4]; @p1 ld.relaxed.gpu.global.b64 %1, [%4+-32768];\n"
                 "@p2 ld.relaxed.gpu.global.b64 %2, [%4+-65536]; @p3 ld.relaxed.gpu.global.b64 %3, [%4+-98304];}"
                 : "+l"(fv[0]), "+l"(fv[1]), "+l"(fv[2]), "+l"(fv[3]) : "l"(a), "r"(n) : "memory");
}
__device__ __forceinline__ cf as_cf(uint64_t v) { cf r; asm("mov.b64 {%0,%1}, %2;" : "=f"(r.x), "=f"(r.y) : "l"(v)); return r; }
template <int H> __device__ __forceinline__ void prescale(float (&u)[64], const float (&d)[128], cf gam) {
#pragma unroll
    for (int i = 0; i < 32; i += 2) {
        const int r = 2 * i + 2 * H;
        c2 v = mul2(c2{{d[r], -d[64 + r]}, {d[r + 1], -d[65 + r]}}, gam);
        if (YS & 2) asm volatile("pmevent 1;" : "+f"(v.a.x), "+f"(v.a.y), "+f"(v.b.x), "+f"(v.b.y));
        u[i] = v.a.x; u[32 + i] = v.a.y; u[i + 1] = v.b.x; u[33 + i] = v.b.y;
    }
}
__device__ __forceinline__ void scan2(const float (&u)[64], cf lam, cf st, const uint8_t* hptr, uint32_t hm, uint32_t hb, uint32_t& keep) {
    uint32_t hp[32];
#pragma unroll
    for (int jj = 0; jj < 4; jj++) {
        cf v[8];
#pragma unroll
        for (int i = 0; i < 8; i++) v[i] = st = cfma(lam, st, {u[8 * jj + i], u[32 + 8 * jj + i]});
        const int o = 8 * jj;
        hp[o] = pk(v[0].x, v[2].x); hp[o + 1] = pk(v[4].x, v[6].x); hp[o + 2] = pk(v[1].x, v[3].x); hp[o + 3] = pk(v[5].x, v[7].x);
        hp[o + 4] = pk(v[0].y, v[2].y); hp[o + 5] = pk(v[4].y, v[6].y); hp[o + 6] = pk(v[1].y, v[3].y); hp[o + 7] = pk(v[5].y, v[7].y);
        hp[o + jj] = (hp[o + jj] & hm) | hb;
        hp[o + 4 + jj] = (hp[o + 4 + jj] & hm) | hb;
        stg128(hptr + (jj >> 1) * 8192 + (jj & 1) * 512, hp[o], hp[o + 1], hp[o + 2], hp[o + 3]);
        stg128(hptr + 16384 + (jj >> 1) * 8192 + (jj & 1) * 512, hp[o + 4], hp[o + 5], hp[o + 6], hp[o + 7]);
        YIELD_S3();
        if (jj > 0) {
#pragma unroll
            for (int i = o - 8; i < o; i += 2) asm volatile("lop3.b32 %0, %0, %1, %2, 0x80;" : "+r"(keep) : "r"(hp[i]), "r"(hp[i + 1]));
        }
    }
}

__device__ __forceinline__ int pos_of(int n) { return (n & 24) + 4 * (n & 1) + ((n >> 1) & 3); }
__device__ __forceinline__ int unit_of(int role, int u, int& slot) {
    const int g = role & 7, w = (role >> 3) & 3, b = role >> 5;
    slot = role >= 128 ? g : (g ? 16 * g + w + 4 * b : 4 * w + b);
    return role >= 128 ? 32 * max(2 * g + u, 1) : (g ? g + 16 * w : ((w & 1) << 4) + ((w & 2) << 2)) + 64 * b + 256 * u;
}
template <int STRIDE> __device__ __forceinline__ bool tags_ok(uint32_t a, uint32_t ep) {
    uint32_t v[4], ok;
#pragma unroll
    for (int i = 0; i < 4; i++) asm volatile("ld.shared.u32 %0, [%1];" : "=r"(v[i]) : "r"(a + i * STRIDE) : "memory");
    asm volatile("{.reg .pred p; .reg .b32 a, b; lop3.b32 a, %1, %2, %5, 0x7e; lop3.b32 b, %3, %4, %5, 0x7e; lop3.b32 a, a, b, 1, 0xa8;\n"
                 "setp.eq.u32 p, a, 0; vote.sync.all.pred p, p, -1; selp.u32 %0, 1, 0, p;}" : "=r"(ok) : "r"(v[0]), "r"(v[1]), "r"(v[2]), "r"(v[3]), "r"(ep));
    return ok;
}
__device__ __forceinline__ void load_w_rows(uint32_t dst, const CUtensorMap* mr, const CUtensorMap* mi, int kap, uint32_t bar) {
    mbar_expect_tx(bar, 16 * WPITCH);
#pragma unroll 1
    for (int i = 0; i < 2; i++, dst += 8 * WPITCH, kap = (512 - kap) & 511) {
        tma2d(dst, mr, (kap * 1026 >> 4) * 2, 0, bar);
        tma2d(dst + 4 * WPITCH, mi, (kap * 1026 >> 4) * 2, 0, bar);
    }
}
__device__ __forceinline__ void prefetch_w_rows(const CUtensorMap* mr, const CUtensorMap* mi, int kap) {
#pragma unroll 1
    for (int i = 0; i < 2; i++, kap = (512 - kap) & 511) {
        asm volatile("cp.async.bulk.prefetch.tensor.2d.L2.global [%0, {%1,%2}];" ::"l"(mr), "r"((kap * 1026 >> 4) * 2), "r"(0) : "memory");
        asm volatile("cp.async.bulk.prefetch.tensor.2d.L2.global [%0, {%1,%2}];" ::"l"(mi), "r"((kap * 1026 >> 4) * 2), "r"(0) : "memory");
    }
}
template <int K0, int K1> __device__ __forceinline__ void store_v(const uint32_t (&vo)[32], const uint8_t* vp, bool p) {
    if (p) {
#pragma unroll
        for (int k = K0; k < K1; k++)
            asm volatile("st.global.v2.b32 [%0], {%1,%2};" ::"l"(vp + (k >> 2) * (1 << 20) + ((k >> 1) & 1) * 8192 + (k & 1) * (4 * 32768)), "r"(vo[2 * k]), "r"(vo[2 * k + 1]) : "memory");
    }
}
#define SB0 1024
__device__ __forceinline__ uint64_t ring_desc(uint32_t sb, uint32_t off, uint32_t lbo, uint32_t swz) {
    uint64_t d;
    asm volatile("{.reg .b32 z; shr.u32 z, %1, 28; mov.b64 %0, {z, z}; add.u64 %0, %0, %2;}" : "=l"(d) : "r"(sb), "l"(mkdesc(SB0 + off, lbo, 1024, swz)));
    return d;
}
struct Ring {
    uint32_t full, rel;
    uint32_t n;
    bool sig;
};
__device__ __forceinline__ void ring_release(const Ring& r, uint32_t o) {
    if (r.sig) asm volatile("mbarrier.arrive.shared::cluster.b64 _, [%0];" ::"r"(r.rel + o) : "memory");
}
__device__ __forceinline__ void peek(uint32_t a, uint32_t ph) { asm volatile("mbarrier.test_wait.parity.shared::cta.b64 pk, [%0], %1;" ::"r"(a), "r"(ph) : "memory"); }
__device__ __forceinline__ void peek_wait(uint32_t a, uint32_t ph, uint32_t& n) {
    asm volatile("{@pk bra DONE;\n"
                 "LOOP: mbarrier.try_wait.parity.shared::cta.b64 pk, [%1], %2; add.u32 %0, %0, 1; setp.gt.or.u32 pk, %0, %3, pk; @!pk bra LOOP;\n"
                 "DONE: }" : "+r"(n) : "r"(a), "r"(ph), "n"(SPIN_LIMIT) : "memory");
}
#define SL(k) ((k) % NST)
#define PH(k) (((k) / NST) & 1)
#define H64 "%64,%65,%66,%67,%68,%69,%70,%71,%72,%73,%74,%75,%76,%77,%78,%79,%80,%81,%82,%83,%84,%85,%86,%87,%88,%89,%90,%91,%92,%93,%94,%95," \
            "%96,%97,%98,%99,%100,%101,%102,%103,%104,%105,%106,%107,%108,%109,%110,%111,%112,%113,%114,%115,%116,%117,%118,%119,%120,%121,%122,%123,%124,%125,%126,%127"
#define WG_MMA "wgmma.mma_async.sync.aligned.m64n128k16.f32.bf16.bf16 "
#define DESC_B(S, j) "mov.b64 {t, hb}, %130; mov.b64 db, {%137 + 2048 * " #S " + 2 * " #j ", hb};\n"
#define MMA_LO(S, j, p) "add.u64 da, %129, 2048 * " #S " + %136 * " #j ";" DESC_B(S, j) WG_MMA "{" L64 "}, da, db, " #p ", 1, 1, %138, 0;\n"
#define MMA_HI(S, j, p) "add.u64 da, %129, 2048 * " #S " + 512 + %136 * " #j ";\n" WG_MMA "{" H64 "}, da, db, " #p ", 1, 1, %138, 0;\n"
#define STEP(S, P, N, ph, pa, pr, X, Y) \
    "wgmma.fence.sync.aligned;\n" MMA_LO(S, 0, pa) MMA_HI(S, 0, pa) \
    "wgmma.commit_group.sync.aligned; wgmma.wait_group.sync.aligned 1; @" #pr " mbarrier.arrive.shared::cluster.b64 _, [%132 + 8 * " #P "];\n" MMA_LO(S, 1, 1) \
    "mbarrier.test_wait.parity.shared::cta.b64 pk, [%131 + 8 * " #N "], " #ph ";\n" MMA_HI(S, 1, 1) MMA_LO(S, 2, 1) X MMA_HI(S, 2, 1) MMA_LO(S, 3, 1) MMA_HI(S, 3, 1) \
    "wgmma.commit_group.sync.aligned;\n" P4A Y "@pk bra GO" #S ";\n" \
    "WAIT" #S ": mbarrier.try_wait.parity.shared::cta.b64 pk, [%131 + 8 * " #N "], " #ph "; add.u32 %128, %128, 1; setp.gt.or.u32 pk, %128, %139, pk; @!pk bra WAIT" #S ";\n" \
    "GO" #S ":\n" P4B
#define P4A
#define P4B
#define P4I
#define P4O
#define STEP_ARGS(TA) \
    : R8(d, 0), R8(d, 8), R8(d, 16), R8(d, 24), R8(d, 32), R8(d, 40), R8(d, 48), R8(d, 56), \
      R8(d, 64), R8(d, 72), R8(d, 80), R8(d, 88), R8(d, 96), R8(d, 104), R8(d, 112), R8(d, 120), "+r"(r.n) \
    : "l"(ha), "l"(hb), "r"(r.full), "r"(r.rel), "r"((uint32_t)r.sig), "r"(wg), \
      "n"(SB0 / 16 + (TA ? 32 << 16 : 1 << 16)), "n"(TA ? 128 : 2), "n"(SB0 / 16 + 1024 + (1 << 16)), "n"(TA), "n"(SPIN_LIMIT) P4O \
    : "memory"
#define STEP_REGS "{.reg .b32 k, t, ph, hb; .reg .b64 da, db; .reg .pred ps, pl, pa, pr;\n" P4I "setp.ne.u32 ps, %133, 0;\n"
#define FIRST_WAIT "FIRST: mbarrier.try_wait.parity.shared::cta.b64 pk, [t], ph; @pk bra START; add.u32 %128, %128, 1; setp.le.u32 pk, %128, %139; @pk bra FIRST; START:\n"
__device__ __forceinline__ void gemm1(float (&d)[128], Ring& r, uint64_t ha, uint64_t hb, int wg) {
    asm volatile(STEP_REGS "mul.lo.u32 k, %134, 15; mov.b32 ph, %134; setp.ne.u32 pl, k, 0; mad.lo.u32 t, %134, 8, %131;\n"
                 "pmevent 1; @pl bar.sync 1, 256;\n" FIRST_WAIT "@pl bra ONE;\n"
                 "LOOP: setp.ne.u32 pa, k, 0; and.pred pr, pa, ps; setp.eq.u32 pl, k, 15;\n"
                 STEP(0, 4, 1, ph, pa, pr, "@pl bar.arrive 1, 256;\n", "@pl bra END;\n")
                 "ONE: setp.ne.u32 pa, k, 15; and.pred pr, pa, ps; setp.eq.u32 pl, k, 30;\n"
                 STEP(1, 0, 2, ph, pa, pr, "@pl bar.arrive 2, 256;\n", "@pl bra END;\n")
                 STEP(2, 1, 3, ph, 1, ps, "", "") STEP(3, 2, 4, ph, 1, ps, "", "") "xor.b32 ph, ph, 1; add.u32 k, k, 5;\n" STEP(4, 3, 0, ph, 1, ps, "", "")
                 "bra LOOP;\n"
                 "END:\n" P4B "}" STEP_ARGS(0));
}
__device__ __forceinline__ void gemm2(float (&d)[128], Ring& r, uint64_t ha, uint64_t hb, int wg) {
    asm volatile(STEP_REGS "mov.b32 k, 0; mov.b32 ph, 0; add.u32 t, %131, 16;\n"
                 "pmevent 1; bar.sync 2, 256;\n" FIRST_WAIT
                 "LOOP: setp.ne.u32 pa, k, 0; and.pred pr, pa, ps; setp.eq.u32 pl, k, 5;\n"
                 STEP(2, 1, 3, ph, pa, pr, "", "") STEP(3, 2, 4, ph, 1, ps, "", "") "xor.b32 ph, ph, 1; add.u32 k, k, 1;\n" STEP(4, 3, 0, ph, 1, ps, "", "")
                 "@pl bra END;\n" STEP(0, 4, 1, ph, 1, ps, "", "") STEP(1, 0, 2, ph, 1, ps, "", "")
                 "bra LOOP;\n"
                 "END: }" STEP_ARGS(1));
}
template <int O, int K, int J> __device__ __forceinline__ void mma_h(float (&y)[128], uint64_t a, uint64_t b) { mma128_ss<O, 1, 0>(y, a + SL(K) * 2048 + O * 8 + 128 * J, b + SL(K) * 2048 + 2 * J, 1); }
template <int O, int K> __device__ __forceinline__ void half_step(float (&y)[128], uint64_t a, uint64_t b) { mma_h<O, K, 0>(y, a, b); mma_h<O, K, 1>(y, a, b); mma_h<O, K, 2>(y, a, b); mma_h<O, K, 3>(y, a, b); }
template <int R, int U> __device__ __forceinline__ void out_piece(float (&y)[128], const uint32_t (&dd)[16], uint32_t x0, uint32_t x1, float* op) {
    const int i = 64 * (R >> 1) + 8 * U + 2 * (R & 1);
    asm("mul.rn.bf16x2 %0, %0, %1;" : "+r"(x0) : "r"(dd[2 * U]));
    asm("mul.rn.bf16x2 %0, %0, %1;" : "+r"(x1) : "r"(dd[2 * U + 1]));
    asm volatile("st.global.v4.f32 [%0], {%1,%2,%3,%4};" ::"l"(op + (32 * (R & 1) + 16 * (R >> 1)) * 2048 + 16 * U),
                 "f"(y[i] + __uint_as_float(x0 << 16)), "f"(y[i + 1] + __uint_as_float(x0 & 0xffff0000u)),
                 "f"(y[i + 4] + __uint_as_float(x1 << 16)), "f"(y[i + 5] + __uint_as_float(x1 & 0xffff0000u)) : "memory");
}
template <int R, int U0> __device__ __forceinline__ void load_x4(uint32_t (&xx)[8], uint32_t xa) {
#pragma unroll
    for (int u = 0; u < 4; u++)
        asm volatile("ld.shared.v2.b32 {%0,%1}, [%2];" : "=r"(xx[2 * u]), "=r"(xx[2 * u + 1]) : "r"((xa ^ (u << 5)) + (3 - R) * 8192 + U0 * 1024) : "memory");
}
__device__ __forceinline__ Ring ring_at(uint32_t sb, int k) {
    Ring r;
    r.n = 0;
    r.full = sb + OFF_BAR + B_FULL;
    asm("mapa.shared::cluster.u32 %0, %1, %2;" : "=r"(r.rel) : "r"(sb + OFF_BAR + B_EMPTY), "r"((threadIdx.x >> 5) & 1));
    r.sig = __shfl_sync(~0u, threadIdx.x & 95, threadIdx.x) == 0;
    return r;
}

template <bool BY_SM> __global__ void __cluster_dims__(2, 1, 1) __launch_bounds__(512, 1)
fused_kernel(const __grid_constant__ CUtensorMap tmX, const __grid_constant__ CUtensorMap tmBre, const __grid_constant__ CUtensorMap tmBim,
             const __grid_constant__ CUtensorMap tmCre, const __grid_constant__ CUtensorMap tmCim, const __grid_constant__ CUtensorMap tmXd,
             const __grid_constant__ CUtensorMap tmUst, const __grid_constant__ CUtensorMap tmVst,
             const __grid_constant__ CUtensorMap tmWr, const __grid_constant__ CUtensorMap tmWi, const __grid_constant__ CUtensorMap tmXa,
             const Params p) {
    extern __shared__ __align__(1024) uint8_t smraw[];
    asm volatile(".reg .pred pk, p0;");
    const int tid = threadIdx.x, rank = blockIdx.x & 1;
    const uint32_t wi = __shfl_sync(~0u, smem_u32(smraw) + (tid >> 5), 0), sb = wi & ~15u, bars = sb + OFF_BAR;
    const int wg = (wi >> 2) & 3, w = wi & 3, lane = tid & 31, g = lane >> 2, q = lane & 3;
    if (wg != 3) asm volatile("barrier.cluster.arrive.relaxed.aligned; barrier.cluster.wait.aligned;" ::: "memory");
    else asm volatile("prefetch.tensormap [%0];" ::"l"(w == 0 ? &tmX : w == 1 ? &tmBre : &tmBim) : "memory");
    int role;
    {
        uint32_t T = blockIdx.x;
        if (BY_SM) asm("mov.u32 %0, %%smid;" : "=r"(T));
        T >>= 1;
        const uint32_t a = ((T - 32) * 37) >> 8;
        asm("{.reg .pred p; setp.lt.u32 p, %1, 62; selp.u32 %0, 4, -58, p; add.u32 %0, %0, %1;\n"
            "setp.lt.u32 p, %1, 60; selp.u32 %0, %2, %0, p; setp.lt.u32 p, %1, 32; selp.u32 %0, %3, %0, p;}"
            : "=&r"(role) : "r"(T), "r"(8 * (T - 31 - 7 * a) + 4 + a), "r"(8 * (T & 7) + (T >> 3)));
        role = 2 * role + rank;
    }
    const bool spare = role >= 128;
    const int tc = ((role >> 3) & 14) + rank, cb = (role >> 1) & 7;
    const int fb = role >> 5, fcb = role & 31, fpos = pos_of(fcb);
    const int nu = role == 128 ? 1 : (fcb || !role ? 2 : 0);

    if (wg == 3) {
        if (elect_one()) {
            const uint32_t b = bars + w * 8;
            STAMP5(57);
            mbar_init(b, 1);
            if (w < 3 && !spare) {
                mbar_expect_tx(b, 32768);
                tma5d(sb + w * 32768 + 16384, &tmX, w * 64, 0, 0, 0, tc, b);
                if (w == 0) { tma4d(sb, &tmBre, 0, 0, 0, cb * 4, b); tma4d(sb + 8192, &tmBim, 0, 0, 0, cb * 4, b); }
                STAMP5(58);
            }
#pragma unroll
            for (int o = 32; o < B_EPOCH; o += 32) mbar_init(b + o, o < B_EMPTY ? 1 : (o < B_STG ? 2 : (o < B_P3M ? 4 : 8)));
            asm volatile("fence.mbarrier_init.release.cluster;" ::: "memory");
        }
        __syncwarp();
        STAMP5(59);
        asm volatile("barrier.cluster.arrive.relaxed.aligned;" ::: "memory");
    }
    if (opaque32(wg) == 3) {
        asm volatile("setmaxnreg.dec.sync.aligned.u32 24;");
        asm volatile("barrier.cluster.wait.aligned;" ::: "memory");
        if (w == 0) {
            if (!spare && elect_one()) {
                STAMP(56);
#pragma unroll 1
                for (int k = 1; k < NST; k++) {
                    if (k >= 3) mbar_expect_tx(bars + B_FULL + k * 8, 32768);
                    tma4d_mc(sb + k * 32768 + rank * 8192, rank ? &tmBim : &tmBre, k * 64, 0, 0, cb * 4, bars + B_FULL + k * 8);
                    if (k >= 3) tma5d(sb + k * 32768 + 16384, &tmX, k * 64, 0, 0, 0, tc, bars + B_FULL + k * 8);
                }
#define RING_WAIT "mbarrier.try_wait.parity.shared::cta.b64 p, [fb + 256], ph; @p bra GO;\n" \
                  "WAIT: mbarrier.try_wait.parity.shared::cta.b64 p, [fb + 256], ph; add.u32 n, n, 1; setp.gt.or.u32 p, n, 32768, p; @!p bra WAIT;\nGO:\n"
#define RING_NEXT "pmevent 1; add.u32 o, o, 8; setp.eq.u32 p, o, 40; selp.u32 o, 0, o, p; @p xor.b32 ph, ph, 1; add.u32 fb, %1, o; shl.b32 t, o, 12; add.u32 da, %0, t;\n"
                asm volatile("{.reg .b32 o, k, kk, c2, da, db, fb, ph, n, t; .reg .pred p;\n"
                             "mov.b32 o, 0; mov.b32 k, 320; mov.b32 kk, 320; mov.b32 c2, 0; mov.b32 ph, 0; mov.b32 n, 0; mov.b32 fb, %1; mov.b32 da, %0; mov.b32 db, %2;\n"
                             "LOOP:\n" RING_WAIT
                             "cp.async.bulk.tensor.5d.shared::cluster.global.mbarrier::complete_tx::bytes [da], [%3, {kk,0,0,0,%5}], [fb];\n"
                             "cp.async.bulk.tensor.4d.shared::cluster.global.mbarrier::complete_tx::bytes.multicast::cluster [db], [%4, {kk,0,c2,%6}], [fb], %7;\n"
                             "mbarrier.arrive.expect_tx.shared::cta.b64 _, [fb], 32768;\n" RING_NEXT
                             "add.u32 db, %2, t; add.u32 k, k, 64; and.b32 kk, k, 1023; shr.u32 c2, k, 9; and.b32 c2, c2, 2; setp.ne.u32 p, k, 2048; @p bra LOOP;}"
                             ::"r"(sb + 16384), "r"(bars + B_FULL), "r"(sb + rank * 8192), "l"(&tmX), "l"(rank ? &tmBim : &tmBre), "r"(tc), "r"(cb * 4), "h"((uint16_t)3) : "memory");
                asm volatile("{.reg .b32 o, k, kk, da, db, fb, hb, ph, n, t; .reg .b64 m, src; .reg .pred p;\n"
                             "mov.b32 o, 16; mov.b32 k, 0; mov.b32 kk, 0; mov.b32 ph, 1; mov.b32 n, 0; add.u32 fb, %1, 16; add.u32 hb, %1, 72; add.u32 da, %0, 65536; add.u32 db, %2, 65536;\n"
                             "mov.b64 m, %3; mov.b64 src, %5;\n"
                             "GROUP: add.u32 t, %8, k;\n"
                             "OWN: mbarrier.try_wait.parity.shared::cta.b64 p, [t], 0; add.u32 n, n, 1; setp.gt.or.u32 p, n, 32768, p; @!p bra OWN;\n"
                             "LOOP:\n" RING_WAIT
                             "cp.async.bulk.shared::cluster.global.mbarrier::complete_tx::bytes [da], [src], 16384, [hb];\n"
                             "cp.async.bulk.tensor.5d.shared::cluster.global.mbarrier::complete_tx::bytes.multicast::cluster [db], [m, {kk,0,0,0,%6}], [fb], %7;\n"
                             "mbarrier.expect_tx.shared::cta.b64 [fb], 16384; mbarrier.arrive.expect_tx.shared::cta.b64 _, [hb], 16384;\n" RING_NEXT
                             "add.u32 db, %2, t; add.u64 src, src, 16384; sub.u64 m, %4, m; add.u32 k, k, 1; shl.b32 kk, k, 5; and.b32 kk, kk, 0x7c0;\n"
                             "and.b32 t, k, 1; mad.lo.u32 hb, t, 8, fb; add.u32 hb, hb, o; add.u32 hb, hb, 40;\n"
                             "and.b32 t, k, 7; setp.ne.u32 p, t, 0; @p bra LOOP; setp.ne.u32 p, k, 32; @p bra GROUP;}"
                             ::"r"(sb), "r"(bars + B_FULL), "r"(sb + 16384 + rank * 8192), "l"(&tmCre), "l"((uint64_t)&tmCre + (uint64_t)&tmCim),
                               "l"(g_H + (size_t)tc * 32 * 16384), "r"(cb * 8 + rank * 4), "h"((uint16_t)3), "r"(bars + B_HOWN) : "memory");
            }
        } else if (opaque32(w) == 1) {
            const unsigned ep = ld_rlx(g_epoch + role * 8) + 1;
            __syncwarp();
            if (elect_one()) {
                asm volatile("st.relaxed.gpu.global.u32 [%0], %1;" ::"l"(g_epoch + role * 8), "r"(ep) : "memory");
                asm volatile("st.shared.u32 [%0], %1;" ::"r"(bars + B_EPOCH), "r"(ep) : "memory");
                mbar_arrive(bars + B_EP);
            }
            int slot;
            const int kap = unit_of(role, 0, slot), kap1 = unit_of(role, 1, slot);
            uint32_t lph = 0;
            if (!spare) mbar_wait(bars + B_STGU, 0);
            STAMP(21);
            const int c0 = fb * 2048 + fpos * 64;
            if (elect_one()) {
                if (!spare) {
#pragma unroll 1
                    for (int r = 4; r < 8; r++) bulk_st(g_X + r * (32 * 16384) + c0 * 2, sb + OFF_P + r * 4096, 128);
                    tma2d_st(&tmUst, c0, 0, sb + OFF_P);
                    bulk_commit();
                    tma2d_st(&tmUst, c0, 64, sb + OFF_P + 8192);
                    bulk_commit();
                    asm volatile("cp.async.bulk.wait_group.read %0;" ::"n"(UH0) : "memory");
                    red_hint(g_cnt);
                }
                mbar_expect_tx(bars + B_FG, 8192);
                bulk_ld(sb + OFF_F, (const uint8_t*)g_tab + TAB_FG, 8192, bars + B_FG);
            }
            STAMP(40);
#pragma unroll 1
            for (int e = 0; e < 4; e++) {
                if (e >= 2) {
                    if (e == nu) {
                        mbar_wait(bars + B_WFREE, 0);
                        if (elect_one()) load_w_rows(sb + OFF_WD, &tmWr, &tmWi, kap1, bars + B_WD);
                    }
                    if (e - 2 < nu) mbar_wait(bars + B_STG, e & 1);
                    STAMPO(23, e - 2);
                    if (e == nu && elect_one()) {
                        const int c = (role ? slot : 256) * 32;
                        tma2d_st(&tmVst, c, 0, sb + OFF_P);
                        tma2d_st(&tmVst, c + 4096, 0, sb + OFF_P + 8192);
                        bulk_commit();
                        if (role) { bulk_wait_read(); red_hint(g_cnt + 64); } else bulk_wait_all();
                    }
                    if (e == 3 && !spare && elect_one()) {
                        mbar_expect_tx(bars + B_FG, 8192);
                        bulk_ld(sb + OFF_F, (const uint8_t*)g_tab + TAB_G + fb * 8192, 8192, bars + B_FG);
                    }
                }
                const uint32_t tg = e < 2 ? lane * 128 + ((((lane >> 1) & 2) ^ (lane & 3)) << 4) + (lane >> 3) * 4 : lane * 64 + (lane & 8) * 4 + (lane & 2) * 8 + (lane & 4) * 2;
                if (spare) {
                    if (e == 1) {
                        wait_cnt(g_cnt, 128 * ep);
                        STAMP(42);
#pragma unroll 1
                        for (int n = 0; n < 4096; n++) {
                            if (elect_one()) {
                                mbar_expect_tx(bars + B_LD, 8 * 16384);
#pragma unroll 1
                                for (int r = 0; r < 8; r++) bulk_ld(sb + r * 16384, g_X + (size_t)r * (32 * 16384), 16384, bars + B_LD);
                            }
                            mbar_wait(bars + B_LD, n & 1);
                            bool ok = true;
#pragma unroll 1
                            for (int r = 0; r < 8; r++) ok &= tags_ok<4096>(sb + r * 16384 + tg, ep);
                            if (ok) break;
                        }
                        if (elect_one()) mbar_arrive(bars + B_RAW);
                    }
                } else {
                    const uint32_t dst = sb + OFF_P + (e & 1) * 16384;
#define X_ST1
#define X_ST2
#define X_RETRY
#define X_ARG
                    asm volatile("{.reg .b32 n, a, v0, v1, v2, v3; .reg .pred p, pe, pu;\n"
                                 "elect.sync _|pe, 0xffffffff; setp.lt.u32 pu, %10, 2; mov.b32 n, 0; pmevent 1;\n"
                                 "POLL: ld.relaxed.gpu.global.u32 v0, [%1]; setp.eq.u32 p, v0, %2; @p bra LOAD;\n"
                                 "nanosleep.u32 20; add.u32 n, n, 1; setp.lt.u32 p, n, 32768; @p bra POLL;\n"
                                 "LOAD:\n" X_ST1 "cp.async.bulk.wait_group.read 0;\n"
                                 "@pe cp.async.bulk.shared::cluster.global.mbarrier::complete_tx::bytes [%3], [%4], 16384, [%5]; @pe mbarrier.arrive.expect_tx.shared::cta.b64 _, [%5], 16384;\n"
                                 "mov.b32 a, 0;\n"
                                 "WAIT: mbarrier.try_wait.parity.shared::cta.b64 p, [%5], %0; @p bra CHECK; add.u32 n, n, 1; setp.lt.u32 p, n, 65536; @p bra WAIT;\n"
                                 "CHECK:\n" X_ST2 "@pu bra FOUR;\n"
                                 "ld.shared.u32 a, [%7]; ld.shared.u32 v0, [%6 + 2048]; ld.shared.u32 v1, [%6 + 6144]; ld.shared.u32 v2, [%6 + 10240]; ld.shared.u32 v3, [%6 + 14336];\n"
                                 "lop3.b32 a, a, v0, %8, 0x7e; lop3.b32 v1, v1, v2, %8, 0x7e; lop3.b32 a, a, v3, %8, 0xf6; or.b32 a, a, v1;\n"
                                 "FOUR: ld.shared.u32 v0, [%6]; ld.shared.u32 v1, [%6 + 4096]; ld.shared.u32 v2, [%6 + 8192]; ld.shared.u32 v3, [%6 + 12288];\n"
                                 "lop3.b32 a, a, v0, %8, 0xf6; lop3.b32 a, a, v1, %8, 0xf6; lop3.b32 v2, v2, v3, %8, 0x7e; lop3.b32 a, a, v2, 1, 0xa8;\n"
                                 "setp.eq.u32 p, a, 0; vote.sync.all.pred p, p, -1; @p bra OK;\n" X_RETRY
                                 "add.u32 n, n, 16; setp.ge.u32 p, n, 65536; @p bra OK; xor.b32 %0, %0, 1; bra LOAD;\n"
                                 "OK: @pe mbarrier.arrive.shared::cta.b64 _, [%9]; pmevent 1; xor.b32 %0, %0, 1;}"
                                 : "+r"(lph)
                                 : "l"(g_cnt + e * 32), "r"(128 * ep), "r"(dst), "l"(g_X + (size_t)(e < 2 ? role + e * 128 : 254 + (fb * 32 + fpos) * 2 + e) * 16384), "r"(bars + B_LD),
                                   "r"(dst + tg), "r"(dst + (e == 3 ? (lane & 1) * 8192 + 32 : 0)), "r"(ep), "r"(bars + B_IN + e * 8), "r"(e) X_ARG : "memory");
                }
                if (e < 2 && elect_one()) {
                    if (e) prefetch_w_rows(&tmWr, &tmWi, kap1);
                    else {
                        if (nu) load_w_rows(sb + OFF_WD, &tmWr, &tmWi, kap, bars + B_WD);
                        if (!spare) {
                            tma2d_st(&tmUst, c0, 128, sb + OFF_P + 16384);
                            tma2d_st(&tmUst, c0, 192, sb + OFF_P + 24576);
                            bulk_commit();
                            if (UH1) bulk_wait_all(); else bulk_wait_read();
                            red_hint(g_cnt + 32);
                        }
                    }
                }
            }
            if (!spare) {
                mbar_wait(bars + B_HOWN + 8, 0);
#pragma unroll 1
                for (int r = 0; r < 4; r++) {
                    if (r == 3) mbar_wait(bars + B_P3M, 0);
                    if (elect_one()) {
                        if (r == 0) { mbar_expect_tx(bars + B_XD, 24576 + 256); mbar_expect_tx(bars + B_XD + 8, 8192); bulk_ld(sb + OFF_LAM, p.dsk + cb * 128, 256, bars + B_XD); }
                        tma4d(sb + OFF_F + (3 - r) * 8192, &tmXd, 0, tc * 128 + 32 * (r & 1) + 16 * (r >> 1), 0, cb * 2, bars + B_XD + (r == 3) * 8);
                    }
                    __nanosleep(PACE_X);
                }
            }
        } else {
            if (w == 2) {
                {
                    const int u = lane >> 4;
                    int slot;
                    const int r0 = unit_of(role, u, slot) + 512 * ((lane >> 1) & 3), r1 = (2048 - r0) & 2047, mir = (lane >> 3) & 1;
                    const unsigned short* wp = (const unsigned short*)((lane & 1) ? p.wi : p.wr);
                    const float a = bf2f(wp[r0 * 513 + mir * 512]), b = bf2f(wp[r1 * 513 + mir * 512]);
                    asm volatile("st.shared.f32 [%0], %1;" ::"r"(sb + OFF_WSP + u * 64 + (lane & 15) * 4), "f"(0.5f * ((lane & 1) ? (mir ? b - a : a - b) : a + b)) : "memory");
                }
                warp_arrive(bars + B_WSP);
            } else if (!spare) {
#pragma unroll 1
                for (int i = 0; i < 8; i++) {
                    if (i >= XA_N0) __nanosleep(XA_PACE);
                    if (elect_one()) {
                        const uint32_t xb = bars + (i < 4 ? B_RAW : B_XIN);
                        if (!(i & 3)) mbar_expect_tx(xb, 16384);
                        tma3d(sb + OFF_F + i * 4096, &tmXa, fcb * 32, 0, 4 * i + fb, xb);
                    }
                }
            }
            if (!spare) {
                if (w == 2 && nu) {
                    int slot;
                    const int kap = unit_of(role, 0, slot);
                    mbar_wait(bars + B_XIN, 0);
                    if (elect_one()) prefetch_w_rows(&tmWr, &tmWi, kap);
                }
                const unsigned ep = get_epoch(bars);
#define CNT_RETRY
#define CNT_ARG
                asm volatile("{.reg .b32 o, k, hb, fb, ca, m, ph, rph, n, t, v0, v1, v2, v3; .reg .b64 src; .reg .pred p, pe;\n"
                             "elect.sync _|pe, 0xffffffff; mov.b32 o, %0; shr.u32 k, %0, 3; sub.u32 k, k, 2; mov.b32 m, 0x107c0; mov.b32 rph, 0; mov.b32 n, 0;\n"
                             "bra NEXT;\n"
                             "LOOP: mbarrier.try_wait.parity.shared::cta.b64 p, [hb], ph; @p bra GO;\n"
                             "WAIT: mbarrier.try_wait.parity.shared::cta.b64 p, [hb], ph; add.u32 n, n, 1; setp.gt.or.u32 p, n, 32768, p; @!p bra WAIT;\n"
                             "GO: ld.shared.u32 v0, [ca]; ld.shared.u32 v1, [ca + 128]; ld.shared.u32 v2, [ca + 256]; ld.shared.u32 v3, [ca + 384];\n"
                             "lop3.b32 v0, v0, v1, %4, 0x7e; lop3.b32 v2, v2, v3, %4, 0x7e; lop3.b32 v0, v0, v2, 1, 0xa8; setp.eq.u32 p, v0, 0; vote.sync.all.pred p, p, -1; @p bra OK;\n"
                             CNT_RETRY "add.u32 n, n, 16; setp.gt.u32 p, n, 32768; @p bra OK;\n"
                             "shl.b32 t, o, 12; add.u32 t, t, %5; mad.wide.u32 src, k, 16384, %6;\n"
                             "@pe mbarrier.arrive.expect_tx.shared::cta.b64 _, [%7], 16384; @pe cp.async.bulk.shared::cluster.global.mbarrier::complete_tx::bytes [t], [src], 16384, [%7];\n"
                             "AGAIN: mbarrier.try_wait.parity.shared::cta.b64 p, [%7], rph; add.u32 n, n, 1; setp.gt.or.u32 p, n, 32768, p; @!p bra AGAIN;\n"
                             "xor.b32 rph, rph, 1; bra GO;\n"
                             "OK: @pe mbarrier.arrive.shared::cta.b64 _, [fb]; pmevent 1;\n"
                             "add.u32 o, o, 16; setp.ge.u32 p, o, 40; @p sub.u32 o, o, 40; add.u32 k, k, 2;\n"
                             "NEXT: shr.u32 m, m, 1; and.b32 ph, m, 1; add.u32 fb, %1, o; mad.lo.u32 hb, o, 2, %2; mad.lo.u32 ca, o, 4096, %3; setp.lt.u32 p, k, 32; @p bra LOOP;}"
                             ::"r"(8 * w), "r"(bars + B_FULL), "r"(bars + B_HL - 16 + w * 8), "r"(sb + (q >> 1) * 8192 + (q & 1) * 512 + g * 1040 + q * 4), "r"(ep),
                               "r"(sb), "l"(g_H + (size_t)tc * 32 * 16384), "r"(bars + B_HR - 16 + w * 8) CNT_ARG : "memory");
                if (w == 3) warp_arrive(bars + B_DONE);
            }
        }
    } else {
        STAMP(55);
        asm volatile("setmaxnreg.inc.sync.aligned.u32 152;");
        STAMP5(60);
        const int t7 = tid & 127, hf = wg - 1;
        const int mi = lane >> 3, gl = lane & 7;
        if (spare && wg != 2) {
            if (tid < 64) { const uint4 v = __ldg((const uint4*)((const uint8_t*)g_tab + TAB_PC) + tid); sts128(sb + OFF_LAM + tid * 16, v.x, v.y, v.z, v.w); }
            bar_sync(1, 256);
            mbar_wait(bars + B_RAW, 0);
            STAMP(0);
#pragma unroll 1
            for (int u = 0; u < nu; u++) {
                int slot;
                const int t = unit_of(role, u, slot) >> 5;
                const uint32_t off = (tid >> 2) * 128 + q * 16;
                float zr[16], zi[16];
#pragma unroll
                for (int k = 0; k < 16; k++) zr[k] = zi[k] = 0.f;
#pragma unroll 1
                for (int r = (t & 1) ? 0 : t >> 1; r < 8 - ((t & 1) ? 0 : (t >> 1) - 1); r += (t & 1) ? 1 : 8 - t) {
                    float4 c;
                    float a[8], b[8];
                    lds128f(sb + OFF_LAM + t * 128 + r * 16, c.x, c.y, c.z, c.w);
                    lds128f(sb + r * 16384 + off, a[0], a[1], a[2], a[3]);
                    lds128f(sb + r * 16384 + off + 64, b[0], b[1], b[2], b[3]);
                    lds128f(sb + r * 16384 + off + 8192, a[4], a[5], a[6], a[7]);
                    lds128f(sb + r * 16384 + off + 8192 + 64, b[4], b[5], b[6], b[7]);
#pragma unroll
                    for (int k = 0; k < 16; k++) {
                        const uint32_t ua = __float_as_uint(a[k >> 1]), ub = __float_as_uint(b[k >> 1]);
                        const float x = __uint_as_float((k & 1) ? ua & 0xffff0000u : ua << 16), y = __uint_as_float((k & 1) ? ub & 0xffff0000u : ub << 16);
                        zr[k] = fmaf(c.x, x, fmaf(c.z, y, zr[k]));
                        zi[k] = fmaf(c.y, x, fmaf(c.w, y, zi[k]));
                    }
                }
                const uint32_t dst = sb + OFF_P + u * 16384 + off;
#pragma unroll
                for (int k = 0; k < 16; k += 8) {
                    sts128(dst + k * 1024, pk(zr[k], zr[k + 1]), pk(zr[k + 2], zr[k + 3]), pk(zr[k + 4], zr[k + 5]), pk(zr[k + 6], zr[k + 7]));
                    sts128(dst + k * 1024 + 64, pk(zi[k], zi[k + 1]), pk(zi[k + 2], zi[k + 3]), pk(zi[k + 4], zi[k + 5]), pk(zi[k + 6], zi[k + 7]));
                }
                fence_async_sm();
                bar_sync(1, 256);
                if (tid == 0) mbar_arrive(bars + B_IN + u * 8);
                STAMPO(1, u);
            }
            return;
        }
        if (wg == 2 && !spare) {
            asm volatile("setmaxnreg.inc.sync.aligned.u32 176;");
            uint32_t f1[16];
            cf tw[8];
            if (TAB_T0) __nanosleep(TAB_T0);
            ldtab<4, 2048>(f1, TAB_F1 + t7 * 16);
            ldtab_cf<16>(tw, TAB_TW1 + (t7 >> 2) * 64);
            const uint32_t ep = get_epoch(bars);
            uint32_t a0 = sb + OFF_P + (8 * w + gl + 32 * (mi >> 1)) * 128 + (((((mi & 1) << 2) | (fpos & 3)) ^ gl) << 4);
            float acc[128];
            const uint64_t dx = opaque(mkdesc(sb + OFF_F, 4096, 512, 2));
            mbar_wait(bars + B_RAW, 0);
            pinu(f1);
            wg_fence();
#pragma unroll
            for (int j = 0; j < 4; j++) mma128_rs<0, 1>(acc, f1[4 * j], f1[4 * j + 1], f1[4 * j + 2], f1[4 * j + 3], dx + j * 64, j);
            wg_commit();
            mbar_wait(bars + B_XIN, 0);
            wg_fence();
            STAMP(20);
#pragma unroll
            for (int j = 0; j < 4; j++) mma128_rs<64, 1>(acc, f1[4 * j], f1[4 * j + 1], f1[4 * j + 2], f1[4 * j + 3], dx + 1024 + j * 64, j);
            wg_commit();
            wg_wait<0>();
            pin(acc);
            pinu(f1);
#pragma unroll 1
            for (int h = 0;; h++) {
                const uint32_t tmask = 2 * q + h == fpos >> 2 ? ~1u : ~0u, tbit = ep & ~tmask;
#pragma unroll
                for (int cl = 0; cl < 2; cl++) {
                    c2 v[8];
#pragma unroll
                    for (int n = 0; n < 8; n++) {
                        const int i = 4 * (4 * n + cl);
                        v[n] = {{acc[i], acc[i + 2]}, {acc[i + 1], acc[i + 3]}};
                    }
                    dft8<true, YP1>(v, tw);
#pragma unroll
                    for (int r = 0; r < 8; r += 2) {
                        uint32_t o0 = pk(v[r].a.x, v[r].b.x), o1 = pk(v[r].a.y, v[r].b.y), o2 = pk(v[r + 1].a.x, v[r + 1].b.x), o3 = pk(v[r + 1].a.y, v[r + 1].b.y);
                        if (cl == 0) { o0 = (o0 & tmask) | tbit; o2 = (o2 & tmask) | tbit; }
                        stsm4((a0 ^ (cl << 4)) + r * 4096, o0, o1, o2, o3);
                    }
                }
                if (h) break;
                a0 ^= 32;
#pragma unroll
                for (int n = 0; n < 8; n++) {
                    asm volatile("mov.b32 %0, %8; mov.b32 %1, %9; mov.b32 %2, %10; mov.b32 %3, %11; mov.b32 %4, %12; mov.b32 %5, %13; mov.b32 %6, %14; mov.b32 %7, %15; pmevent 1;"
                                 : "=&f"(acc[16 * n]), "=&f"(acc[16 * n + 1]), "=&f"(acc[16 * n + 2]), "=&f"(acc[16 * n + 3]), "=&f"(acc[16 * n + 4]), "=&f"(acc[16 * n + 5]), "=&f"(acc[16 * n + 6]), "=&f"(acc[16 * n + 7])
                                 : "f"(acc[16 * n + 8]), "f"(acc[16 * n + 9]), "f"(acc[16 * n + 10]), "f"(acc[16 * n + 11]), "f"(acc[16 * n + 12]), "f"(acc[16 * n + 13]), "f"(acc[16 * n + 14]), "f"(acc[16 * n + 15]));
                }
            }
            fence_async_sm();
            warp_arrive(bars + B_STGU);
            bar_sync(3, 128);
            asm volatile("setmaxnreg.dec.sync.aligned.u32 152;");
            bar_arrive(7, 256);
        }
        if (wg == 1) {
            if (LAM_T0) __nanosleep(LAM_T0);
            const int cl = tid & 127, ch = (cl >> 6) * 512 + ((cl >> 3) & 1) * 256 + cb * 32 + ((cl >> 4) & 3) * 8 + (cl & 7);
            const float lr = bf2f(*(const unsigned short*)padd(p.lre, 2 * ch)), li = bf2f(*(const unsigned short*)padd(p.lim, 2 * ch));
            const float dt = __bfloat162float(__float2bfloat16(expf(bf2f(*(const unsigned short*)padd(p.ldt, 2 * ch)))));
            const float an = dt * li, th = an * 0.318309873342514f;
            float sn, cs, inv;
            sincospif(fmaf(rintf(0.5f * th), -2.f, th) + fmaf(an, 1.2841276653e-8f, fmaf(an, 0.318309873342514f, -th)), &sn, &cs);
            const float ex = expf(dt * lr), br = ex * cs, bi = ex * sn;
            asm("rcp.approx.f32 %0, %1;" : "=f"(inv) : "f"(lr * lr + li * li));
            inv += inv;
            const float cr = ((br - 1.f) * lr + bi * li) * inv, ci = (bi * lr - (br - 1.f) * li) * inv;
            sts128(sb + OFF_LAM + cl * 16, __float_as_uint(br), __float_as_uint(-bi), __float_as_uint(cr), __float_as_uint(-ci));
            mbar_wait(bars + B_EP, 0);
            bar_sync(8, 128);
            if (tid == 128) mbar_arrive(bars + B_LAM);
        }
        if (wg != 2) {
        if (wg == 0) bar_sync(4, 128); else bar_sync(7, 256);
        asm volatile("setmaxnreg.inc.sync.aligned.u32 160;");
        if (wg == 0) bar_sync(4, 128);
        float d[128];
        STAMPW(0, 10);
        Ring rg = ring_at(sb, role * 66 + wg * 16);
        cf lam[2];
        unsigned ep;
        gemm1(d, rg, ring_desc(sb, 0, 16, 1), ring_desc(sb, 16384, 16, 1), wg);
        const uint32_t lama = sb + OFF_LAM + wg * 1024 + w * 256 + (fresh_lane() & 28) * 4;
        mbar_wait_fast(bars + B_LAM, 0);
        lam[0] = lds_cf(lama); lam[1] = lds_cf(lama + 128);
        asm volatile("ld.shared.u32 %0, [%1];" : "=r"(ep) : "r"(bars + B_EPOCH) : "memory");
        asm volatile("setmaxnreg.inc.sync.aligned.u32 176;");
        cf L[2] = {lam[0], lam[1]};
#pragma unroll
        for (int i = 0; i < 4; i++) { L[0] = csq(L[0]); L[1] = csq(L[1]); }
        asm volatile("" : "+f"(L[0].x), "+f"(L[0].y), "+f"(L[1].x), "+f"(L[1].y)::"memory");
        wg_wait<0>();
        ring_release(rg, 8 * wg);
        pin(d);
        STAMPW(1, 11);
        {
            const int lane = fresh_lane(), g = lane >> 2, q = lane & 3, mi = lane >> 3, gl = lane & 7;
            cf f[2], fb2[2];
#pragma unroll
            for (int i = 0; i < 17; i++) {
#pragma unroll
                for (int h = 0; h < 2; h++) {
                    const int r = 4 * (i >> 1) + 2 * h + (i & 1), r2 = 32 + 4 * ((i - 1) >> 1) + 2 * h + ((i - 1) & 1);
                    if (i < 16) f[h] = i ? cfma(lam[h], f[h], {d[r], -d[64 + r]}) : cf{d[r], -d[64 + r]};
                    if (i > 0) fb2[h] = i > 1 ? cfma(lam[h], fb2[h], {d[r2], -d[64 + r2]}) : cf{d[r2], -d[64 + r2]};
                    if (i && (h || !(YS & 8))) YIELD_S1();
                }
            }
            const uint8_t* cbase = (const uint8_t*)g_carry + (tc * 16 + wg * 8 + cb) * 512 + w * 64;
            const uint8_t* cptr = padd(cbase, g * 8);
            const unsigned tag = ep & 15u;
#pragma unroll
            for (int h = 0; h < 2; h++) { f[h] = cfma(L[h], f[h], fb2[h]); L[h] = csq(L[h]); }
            cf s0[2], s1[2], s2[2];
#pragma unroll
            for (int h = 0; h < 2; h++) {
                s0[h] = {__shfl_sync(~0u, f[h].x, 0, 4), __shfl_sync(~0u, f[h].y, 0, 4)};
                s1[h] = {__shfl_sync(~0u, f[h].x, 1, 4), __shfl_sync(~0u, f[h].y, 1, 4)};
                s2[h] = {__shfl_sync(~0u, f[h].x, 2, 4), __shfl_sync(~0u, f[h].y, 2, 4)};
            }
#pragma unroll
            for (int h = 0; h < 2; h++) {
                s1[h] = cfma(L[h], s0[h], s1[h]);
                s2[h] = cfma(L[h], s1[h], s2[h]);
                f[h] = cfma(L[h], s2[h], f[h]);
                asm volatile("{.reg .pred p; .reg .b64 a; setp.eq.u32 p, %3, 3; mov.b64 a, {%1,%2}; @p st.relaxed.gpu.global.b64 [%0], a;}" ::"l"(cptr + h * 256),
                             "r"((__float_as_uint(f[h].x) & ~15u) | tag), "f"(f[h].y), "r"(q) : "memory");
            }
            STAMPX(2, 12);
            cf gam = lds_cf(lama + 8);
            cf st = csel(q & 2, csel(q & 1, s2[0], s1[0]), csel(q & 1, s0[0], {0.f, 0.f}));
            const cf st1 = csel(q & 2, csel(q & 1, s2[1], s1[1]), csel(q & 1, s0[1], {0.f, 0.f}));
            cptr = padd(cbase - 4 * 8192, (3 - mi) * 8192 + gl * 8);
            const int nprev = tc - 1 - mi;
            const uint8_t* hptr = padd(g_H + (size_t)(tc * 32 + wg * 16 + (cb & 6)) * 16384 + ((cb & 1) * 4 + w) * 1024, g * 64 + ((q ^ (g >> 1)) << 4));
            const uint32_t hm = 4 * (g & 1) + (q ^ (g >> 1)) == (cb & 1) * 4 + w ? ~1u : ~0u;
            float u[64];
            uint64_t fv[4] = {tag, tag, tag, tag};
            prescale<0>(u, d, gam);
            gather(fv, cptr, nprev);
#pragma unroll 1
            for (int h = 0;; h++) {
                const cf L2 = csq(L[0]), M = csq(L2);
                cf M4 = csq(csq(M));
                M4 = {__shfl_sync(~0u, M4.x, 4 * gl), __shfl_sync(~0u, M4.y, 4 * gl)};
                cf lq = cmul(gam, cmul(csel(q & 1, L[0], {1.f, 0.f}), csel(q & 2, L2, {1.f, 0.f})));
                st = cmul(gam, st);
                asm volatile("pmevent 1;" : "+f"(lq.x), "+f"(lq.y), "+f"(st.x), "+f"(st.y));
#pragma unroll 1
                for (unsigned n = 0; __any_sync(~0u, (((uint32_t)fv[0] ^ tag) | ((uint32_t)fv[1] ^ tag) | ((uint32_t)fv[2] ^ tag) | ((uint32_t)fv[3] ^ tag)) & 15u) && n < SPIN_LIMIT; n++) gather(fv, cptr, nprev);
                if (!h) STAMPX(53, 54);
                cf P = as_cf(fv[3]), pj[4];
#pragma unroll
                for (int a = 2; a >= 0; a--) P = cfma(M4, P, as_cf(fv[a]));
                cptr += 256;
                asm volatile("" : "+f"(P.x), "+f"(P.y)::"memory");
                gather(fv, cptr, h ? -1 : nprev);
#pragma unroll
                for (int j = 3; j >= 0; j--) pj[j] = {__shfl_sync(~0u, P.x, g + 8 * j), __shfl_sync(~0u, P.y, g + 8 * j)};
                st = cfma(lq, cfma(M, cfma(M, cfma(M, pj[3], pj[2]), pj[1]), pj[0]), st);
                if (!h) STAMPX(3, 13);
                uint32_t keep = sb >> 28;
                scan2(u, lam[0], st, hptr, hm, ep & ~hm, keep);
                warp_arrive(bars + B_HOWN + wg * 16 + h * 8 + keep);
                if (h) break;
                STAMPW(4, 14);
                if (wg == 1 && nu) bar_sync(9, 256);
                lds128f(lama + 128, lam[0].x, lam[0].y, gam.x, gam.y);
                st = st1;
                L[0] = L[1];
                hptr += 8 * 16384;
                prescale<1>(u, d, gam);
            }
            STAMPW(5, 15);
        }
        if (wg == 0) bar_sync(4, 128); else bar_sync(8, 128);
        if (wg == 0) {
            asm volatile("setmaxnreg.dec.sync.aligned.u32 160;");
            float y[128];
            rg = ring_at(sb, role * 66 + 32);
            STAMP(6);
            STAMP(7);
            const uint64_t dA = ring_desc(sb, 0, 512, 2), dB = ring_desc(sb, 16384, 16, 1);
            gemm2(y, rg, dA, dB, 0);
            asm volatile("setmaxnreg.inc.sync.aligned.u32 184;");
            const int lane = fresh_lane(), g = lane >> 2, q = lane & 3;
            const int pg = 2 * (g & 3) + (g >> 2);
            float* op = (float*)padd(p.out + (size_t)(tc * 128 + 64 * (w & 1) + 8 * (w >> 1)) * 2048 + 1024 + cb * 128, pg * 8192 + q * 16);
            const uint32_t xa = sb + OFF_F + (16 * (w & 1) + 8 * (w >> 1) + pg) * 128 + (((q >> 1) ^ pg) << 4) + (q & 1) * 8;
#define HALF0(k) wg_fence(); peek(k < 63 ? rg.full + SL(k + 1) * 8 : bars + B_XD, PH(k + 1)); half_step<0, k>(y, dA, dB); wg_commit(); peek_wait(k < 63 ? rg.full + SL(k + 1) * 8 : bars + B_XD, PH(k + 1), rg.n);
            HALF0(60) HALF0(61) HALF0(62) HALF0(63)
            const uint64_t dB2 = ring_desc(sb >> 1, 16384, 16, 1);
            uint32_t xa0[8], xa1[8], dd[16];
#pragma unroll
            for (int i = 0; i < 8; i++) asm volatile("ld.shared.v2.b32 {%0,%1}, [%2];" : "=r"(dd[2 * i]), "=r"(dd[2 * i + 1]) : "r"(sb + OFF_LAM + q * 8 + 32 * i) : "memory");
            load_x4<0, 0>(xa0, xa);
            wg_fence();
            half_step<64, 64 - SKEW>(y, dA, dB2);
            wg_commit();
            wg_wait<1>();
#pragma unroll
            for (int i = 0; i < 64; i++) asm volatile("" : "+f"(y[i])::"memory");
            STAMP(16);
#define MM(n) if (4 + (n) < 4 * SKEW) { wg_fence(); mma_h<64, 65 - SKEW + (n) / 4, (n) % 4>(y, dA, dB2); mma_h<64, 65 - SKEW + (n) / 4, (n) % 4 + 1>(y, dA, dB2); }
#define OUT4(R, U, X, n) out_piece<R, U>(y, dd, X[0], X[1], op); MM(n) out_piece<R, U + 1>(y, dd, X[2], X[3], op); MM(n + 2) \
                         out_piece<R, U + 2>(y, dd, X[4], X[5], op); MM(n + 4) out_piece<R, U + 3>(y, dd, X[6], X[7], op); MM(n + 6)
            load_x4<0, 4>(xa1, xa);
            OUT4(0, 0, xa0, 0)
            load_x4<1, 0>(xa0, xa);
            OUT4(0, 4, xa1, 8)
            wg_commit();
            load_x4<1, 4>(xa1, xa);
            OUT4(1, 0, xa0, 16)
            load_x4<2, 0>(xa0, xa);
            OUT4(1, 4, xa1, 16)
            STAMP(18);
            wg_wait<0>();
#pragma unroll
            for (int i = 64; i < 128; i++) asm volatile("" : "+f"(y[i])::"memory");
            STAMP(8);
            load_x4<2, 4>(xa1, xa);
            mbar_wait_fast(bars + B_XD + 8, 0);
            OUT4(2, 0, xa0, 16)
            load_x4<3, 0>(xa0, xa);
            OUT4(2, 4, xa1, 16)
            load_x4<3, 4>(xa1, xa);
            OUT4(3, 0, xa0, 16)
            OUT4(3, 4, xa1, 16)
            STAMP(9);
            return;
        }
        asm volatile("setmaxnreg.dec.sync.aligned.u32 152;");
        } else {
        if (nu) {
            cf T[8];
            ldtab_cf<2048>(T, TAB_T + t7 * 16);
            const uint32_t ep = get_epoch(bars);
            const int ka = pos_of(t7 >> 2);
            asm volatile("setp.eq.u32 p0, %0, 0;" ::"r"(__shfl_sync(~0u, t7, lane)));
            mbar_wait(bars + B_WSP, 0);
            mbar_wait(bars + B_FG, 0);
            uint32_t wd[4], wm[4], vo[32];
            const uint8_t* vp;
            int slot;
            const int kap0 = unit_of(role, 0, slot), al = 2 * kap0;
            const int kap1 = __shfl_sync(~0u, unit_of(role, 1, slot), 0);
            slot = __shfl_sync(~0u, slot, 0);
            cf be1 = twid(kap0 + 512 * q, 2048), be2 = csq(be1), be3 = cmul(be1, be2);
#pragma unroll
            for (int j = 0; j < 4; j++) {
                wd[j] = sb + OFF_WD + ((j + q) & 3) * WPITCH + (al & 15) + 2 * ka + 64 * q;
                wm[j] = sb + OFF_WM + (((role ? 3 : 4) - j - q) & 3) * WPITCH + (-al & 15) + 1024 - 2 * ka - 64 * q;
                wd[j] = __shfl_sync(~0u, wd[j], lane);
            }
#pragma unroll 1
            for (int u = 0; u < nu; u++) {
                const uint32_t buf = sb + OFF_P + u * 16384;
                float acc[64], za[32], zb[32], ya[32], yb[32], vv[64];
                const uint64_t dF = opaque(mkdesc(sb + OFF_F, 16, 1024, 1)), dB = opaque(mkdesc(buf, 4096, 512, 2));
                mbar_wait(bars + B_IN + u * 8, 0);
                if (!role) {
                    const uint32_t z = buf + w * 1024 + (fresh_lane() >> 2) * 128 + 64 + (fresh_lane() & 3) * 16;
#pragma unroll
                    for (int i = 0; i < 4; i++) sts128(z + i * 4096, 0, 0, 0, 0);
                    fence_async_sm();
                    bar_sync(3, 128);
                }
                STAMP3(22);
                wg_fence();
#pragma unroll
                for (int j = 0; j < 4; j++) mma128_ss<0, 0, 1>(acc, dF + j * 2, dB + j * 64, j);
                wg_commit();
                if (u) {
                    const uint32_t va = sb + OFF_P + (((uint32_t)(uintptr_t)vp - (uint32_t)(uintptr_t)g_X) >> 9 & 0x7c0) + ((uint32_t)(uintptr_t)vp & 31) + (fresh_lane() & 4) * 8;
                    bar_sync(3, 128);
#pragma unroll
                    for (int k = 0; k < 16; k++) sts64(va + ((k >> 1) & 1) * 8192 + (k >> 2) * 2048 + (k & 1) * 256, vo[2 * k], vo[2 * k + 1]);
                    fence_async_sm();
                    warp_arrive(bars + B_STG);
                    if (!role) { const uint32_t t = wm[0]; wm[0] = wm[1]; wm[1] = wm[2]; wm[2] = wm[3]; wm[3] = t; }
                }
                STAMP3(39);
                wg_wait<0>();
                pin(acc);
                STAMP3(30);
                uint32_t af[16], ag[16];
#pragma unroll
                for (int k = 0; k < 8; k++) {
                    uint32_t(&o)[16] = k < 4 ? af : ag;
                    const int c = k & 3;
#pragma unroll
                    for (int b = 0; b < 2; b++) {
                        const int i = 4 * (4 * ((k >> 2) * 2 + b) + c);
                        c2 x = mul2(c2{{acc[i], acc[i + 2]}, {acc[i + 1], acc[i + 3]}}, c2{T[2 * c], T[2 * c + 1]});
                        o[4 * c + b] = pk(x.a.x, x.a.y);
                        o[4 * c + 2 + b] = pk(x.b.x, x.b.y);
                    }
                    asm volatile("" : "+r"(o[4 * c]), "+r"(o[4 * c + 1]), "+r"(o[4 * c + 2]), "+r"(o[4 * c + 3])::"memory");
                    wg_fence();
                    mma64_rs<0>(k < 4 ? za : zb, o[4 * c], o[4 * c + 1], o[4 * c + 2], o[4 * c + 3], dF + c * 2, c);
                }
                wg_commit();
                STAMP3(31);
                mbar_wait(bars + B_WD, u & 1);
                uint32_t wr[16];
#pragma unroll
                for (int i = 0; i < 16; i++) wr[i] = lds16(wd[i >> 2] + 256 * ((i >> 1) & 1) + (i & 1) * 4 * WPITCH);
                wg_wait<0>();
                pin(za);
                pin(zb);
                pinu(af);
                pinu(ag);
                STAMP3(32);
#pragma unroll
                for (int jb = 0; jb < 4; jb++) {
                    const int i = 8 * jb;
                    c2 s0 = {{za[i], za[i + 4]}, {za[i + 1], za[i + 5]}}, s2 = {{za[i + 2], za[i + 6]}, {za[i + 3], za[i + 7]}};
                    c2 s1 = {{zb[i], zb[i + 4]}, {zb[i + 1], zb[i + 5]}}, s3 = {{zb[i + 2], zb[i + 6]}, {zb[i + 3], zb[i + 7]}};
                    c2 W[4];
                    auto wcvt = [&](int j) {
                        asm volatile("shl.b32 %0, %4, 16; shl.b32 %1, %5, 16; shl.b32 %2, %6, 16; shl.b32 %3, %7, 16;"
                                     : "=&f"(W[j].a.x), "=&f"(W[j].a.y), "=&f"(W[j].b.x), "=&f"(W[j].b.y) : "r"(wr[4 * j]), "r"(wr[4 * j + 1]), "r"(wr[4 * j + 2]), "r"(wr[4 * j + 3]));
                        if ((jb & 1) == 0)
                            asm volatile("@p0 ld.shared.v2.f32 {%0,%1}, [%2];" : "+f"(W[j].a.x), "+f"(W[j].a.y) : "r"(sb + OFF_WSP + u * 64 + jb * 16 + j * 8));
                        if (jb < 3) {
#pragma unroll
                            for (int k = 4 * j; k < 4 * j + 4; k++) {
                                const int e = (k >> 1) & 1, pl = (k & 1) * 4 * WPITCH;
                                wr[k] = jb == 0 ? lds16(wd[j] + 512 + 256 * e + pl) : lds16(wm[j] - 512 * (jb - 1) - 256 * e + pl);
                            }
                        }
                        if (jb >= 2) { W[j].a.y = -W[j].a.y; W[j].b.y = -W[j].b.y; }
                    };
                    wcvt(0);
                    s2 = mul2(s2, be1);
                    s1 = fma2(s1, be2, s0);
                    wcvt(1);
                    s3 = fma2(s3, be3, s2);
                    { const c2 x = twm2(s0, s1), y = twm2(s2, s3); s0 = s1; s2 = s3; s1 = x; s3 = y; }
                    wcvt(2);
                    bfly<0>(s0, s2); bfly_mi<0>(s1, s3);
                    wcvt(3);
                    s0 = mul2(s0, W[0]); s1 = mul2(s1, W[1]);
                    bfly_tw<0>(s0, s2, W[2], s1, s3, W[3]);
                    bfly<0>(s0, s1); bfly_mi<0>(s2, s3);
                    af[4 * jb] = pk(s0.a.x, s0.b.x); af[4 * jb + 1] = pk(s3.a.x, s3.b.x); af[4 * jb + 2] = pk(s0.a.y, s0.b.y); af[4 * jb + 3] = pk(s3.a.y, s3.b.y);
                    ag[4 * jb] = pk(s1.a.x, s1.b.x); ag[4 * jb + 1] = pk(s2.a.x, s2.b.x); ag[4 * jb + 2] = pk(s1.a.y, s1.b.y); ag[4 * jb + 3] = pk(s2.a.y, s2.b.y);
                }
                pinu(af);
                pinu(ag);
                warp_arrive(bars + B_WFREE);
                wg_fence();
#pragma unroll
                for (int j = 0; j < 4; j++) mma64_rs<1>(ya, af[4 * j], af[4 * j + 1], af[4 * j + 2], af[4 * j + 3], dF + j * 128, j);
                wg_commit();
#pragma unroll
                for (int j = 0; j < 4; j++) mma64_rs<1>(yb, ag[4 * j], ag[4 * j + 1], ag[4 * j + 2], ag[4 * j + 3], dF + j * 128, j);
                wg_commit();
                STAMP3(33);
                {
                    const uint32_t a0 = buf + (mi & 1) * 4096 + (16 * w + 8 * (mi >> 1) + gl) * 64 + ((gl >> 1) << 4);
#pragma unroll
                    for (int h = 0; h < 2; h++) {
                        if (h == 0) { wg_wait<1>(); pin(ya); pinu(af); STAMP3(34); } else { wg_wait<0>(); pin(yb); pinu(ag); }
                        const float(&yy)[32] = h ? yb : ya;
#pragma unroll
                        for (int c = 0; c < 4; c++) {
                            const int i = 8 * ((c + 2 * h) & 3), k = 8 * ((c + 2 * h + 1) & 3) + 2;
                            c2 x = {cmulc({yy[i], yy[i + 1]}, T[2 * c]), cmulc({yy[k], yy[k + 1]}, T[2 * c])};
                            fin<1>(x);
                            c2 y = {cmulc({yy[i + 4], yy[i + 5]}, T[2 * c + 1]), cmulc({yy[k + 4], yy[k + 5]}, T[2 * c + 1])};
                            fin<1>(y);
                            stsm4((a0 ^ (c << 4)) + h * 8192, pk(x.a.x, y.a.x), pk(x.b.x, y.b.x), pk(x.a.y, y.a.y), pk(x.b.y, y.b.y));
                        }
                    }
                }
                STAMP3(38);
                fence_async_sm();
                bar_sync(3, 128);
                wg_fence();
#pragma unroll
                for (int j = 0; j < 4; j++) mma128_ss<0, 1, 1>(vv, dF + j * 128, dB + j * 64, j);
                wg_commit();
                STAMP3(35);
                if (u && !spare) bar_arrive(9, 256);
                const int lane = fresh_lane(), g = lane >> 2, q = lane & 3;
                vp = padd(g_X + (4 << 20) + w * (8 * 32768) + (role ? u : 1) * 16384 + slot * 64,
                                         (g >> 1) * 32768 + (role ? g & 1 : u) * 32 + (((q ^ (slot >> 1)) & 1) << 4) + (q >> 1) * 8);
                const uint32_t tmask = (((g & 1) == ((slot >> 3) & 1) || !role) && q == ((slot >> 1) & 2)) ? ~1u : ~0u, tbit = (ep ^ (role + u ? 0 : g)) & ~tmask;
                be1 = twid(kap1 + 512 * q, 2048); be2 = csq(be1); be3 = cmul(be1, be2);
                asm volatile("pmevent 1;" : "+f"(be1.x), "+f"(be1.y), "+f"(be2.x), "+f"(be2.y), "+f"(be3.x), "+f"(be3.y), "+l"(vp)::"memory");
                wg_wait<0>();
                pin(vv);
                STAMP3(36);
#pragma unroll
                for (int k = 0; k < 16; k++) {
                    const int i = 8 * (k >> 1) + 2 * (k & 1);
                    vo[2 * k] = (pk(vv[i], vv[i + 1]) & tmask) | tbit;
                    vo[2 * k + 1] = pk(vv[i + 4], vv[i + 5]);
                }
                pinu(vo);
            }
            if (!role) mbar_wait(bars + B_IN + 16, 0);
            warp_arrive(bars + B_STG);
            const bool odd = fresh_lane() & 4;
            store_v<0, 4>(vo, vp, role || !odd);
            asm volatile("@p0 red.relaxed.gpu.global.add.u32 [%0], 1;" ::"l"(g_cnt + 32 + nu * 32) : "memory");
            store_v<4, 16>(vo, vp, role || odd);
        }
        if (spare) return;
        }
        {
            constexpr int Y = YP3;
            uint32_t sp[8];
            cf tw[8];
            ldtab<2, 2048>(sp, TAB_SP + fb * 4096 + t7 * 16);
            ldtab_cf<16>(tw, TAB_TW3 + fb * 2048 + (t7 >> 2) * 64);
            const uint64_t dF = opaque(mkdesc(sb + OFF_F, 16, 1024, 1)), dB = opaque(mkdesc(sb + OFF_P + hf * 8192, 1024, 256, 3));
            const uint8_t* op = padd(p.out + (1024 + fb) * 2048 + fcb * 32 + hf * 16, (t7 >> 2) * 32768 + (q >> 1) * 16 + (q & 1) * 32);
            float acc[64], out[64];
            mbar_wait(bars + B_IN + 24, 0);
            mbar_wait(bars + B_FG, 1);
            STAMP(25);
            pinu(sp);
            wg_fence();
#pragma unroll
            for (int j = 0; j < 4; j++) {
                const uint64_t db = dB + (j >> 1) * 1024 + (j & 1) * 32;
                mma112_ss(acc, dF + j * 2, db + 64, j);
                if (j & 1) mma16_rs(acc, 0u, sp[2 * j], 0u, sp[2 * j + 1], db, 1);
                else mma16_rs(acc, sp[2 * j], 0u, sp[2 * j + 1], 0u, db, j);
            }
            wg_commit();
            wg_wait<0>();
            pin(acc);
            pinu(sp);
            warp_arrive(bars + B_P3M);
            if (!hf) bar_sync(5, 256);
#pragma unroll
            for (int cl = 0; cl < 2; cl++) {
                c2 z[8];
#pragma unroll
                for (int n = 0; n < 8; n++) {
                    const int i = 4 * (2 * n + cl);
                    z[n] = {{acc[i], acc[i + 2]}, {acc[i + 1], acc[i + 3]}};
                }
                z[0] = {{z[0].a.x + z[0].a.y, z[0].a.x - z[0].a.y}, {z[0].b.x + z[0].b.y, z[0].b.x - z[0].b.y}};
                z[4] = mul2(z[4], tw[4]);
                fin<Y>(z[0], z[4]);
#pragma unroll
                for (int n = 1; n < 4; n++) {
                    const cf iw = n == 1 ? cf{0.38268343236508977f, 0.92387953251128674f}
                                         : (n == 2 ? cf{0.70710678118654752f, 0.70710678118654752f} : cf{0.92387953251128674f, 0.38268343236508977f});
                    c2 y = mul2(z[n], tw[n]);
                    fin<Y>(y);
                    const cf t = {tw[8 - n].x, -tw[8 - n].y};
                    c2 E = fma2(c2{{z[8 - n].a.x, -z[8 - n].a.y}, {z[8 - n].b.x, -z[8 - n].b.y}}, t, y);
                    fin<Y>(E);
                    z[n] = fma2(twm2(y, E), iw, E);
                    fin<Y>(z[n]);
                    z[8 - n] = {{fmaf(2.f, E.a.x, -z[n].a.x), fmaf(-2.f, E.a.y, z[n].a.y)}, {fmaf(2.f, E.b.x, -z[n].b.x), fmaf(-2.f, E.b.y, z[n].b.y)}};
                }
                dft8<false, Y>(z, tw);
#pragma unroll
                for (int m = 0; m < 8; m++) {
                    out[8 * m + 2 * cl] = z[m].a.x; out[8 * m + 2 * cl + 1] = z[m].b.x;
                    out[8 * m + 4 + 2 * cl] = z[m].a.y; out[8 * m + 5 + 2 * cl] = z[m].b.y;
                }
            }
            pin(out);
            if (hf) bar_arrive(5, 256);
            if (hf) STAMP(26);
#pragma unroll
            for (int m = 0; m < 16; m++) {
                asm volatile("st.global.v4.f32 [%0], {%1,%2,%3,%4};" ::"l"(op + (m - 8) * (1 << 20)), "f"(out[4 * m]), "f"(out[4 * m + 1]), "f"(out[4 * m + 2]), "f"(out[4 * m + 3]) : "memory");
                if (PACE_O && m < 15 && m % PACE_ON == PACE_ON - 1)
                    asm volatile("{.reg .pred p; mbarrier.test_wait.parity.shared::cta.b64 p, [%0], 0; @!p nanosleep.u32 %1;}" ::"r"(bars + B_DONE), "n"(PACE_O) : "memory");
            }
            STAMP(27);
        }
    }
}

typedef CUresult (*EncodeFn)(CUtensorMap*, CUtensorMapDataType, cuuint32_t, void*, const cuuint64_t*, const cuuint64_t*, const cuuint32_t*,
                             const cuuint32_t*, CUtensorMapInterleave, CUtensorMapSwizzle, CUtensorMapL2promotion, CUtensorMapFloatOOBfill);

static CUtensorMap make_map(EncodeFn enc, const void* ptr, int rank, const cuuint64_t* dims, const cuuint64_t* strides, const cuuint32_t* box,
                            CUtensorMapSwizzle swz, CUtensorMapL2promotion promo, CUtensorMapDataType dt = CU_TENSOR_MAP_DATA_TYPE_BFLOAT16) {
    CUtensorMap m;
    const cuuint32_t es[5] = {1, 1, 1, 1, 1};
    enc(&m, dt, rank, const_cast<void*>(ptr), dims, strides, box, es, CU_TENSOR_MAP_INTERLEAVE_NONE, swz, promo,
        CU_TENSOR_MAP_FLOAT_OOB_FILL_NONE);
    return m;
}

extern "C" void kernel_launch(void* const* d_in, const int* in_sizes, int n_in, void* d_out, int out_size) {
    void* fn = nullptr;
    cudaDriverEntryPointQueryResult qr;
    cudaGetDriverEntryPoint("cuTensorMapEncodeTiled", &fn, cudaEnableDefault, &qr);
    EncodeFn enc = (EncodeFn)fn;
    void* pX;
    cudaGetSymbolAddress(&pX, g_X);
    const CUtensorMapL2promotion P256 = CU_TENSOR_MAP_L2_PROMOTION_L2_256B, P0 = CU_TENSOR_MAP_L2_PROMOTION_NONE;

    const cuuint64_t dX[5] = {1024, 2, 4, 16, 16}, sX[4] = {2048, 32 * 2048, 2 * 2048, 128 * 2048};
    const cuuint32_t bX[5] = {64, 2, 4, 16, 1};
    CUtensorMap tmX = make_map(enc, d_in[3], 5, dX, sX, bX, CU_TENSOR_MAP_SWIZZLE_128B, P256);
    const cuuint64_t dXd[4] = {64, 2048, 2, 16}, sXd[3] = {2048, 64 * 2048, 128};
    const cuuint32_t bXd[4] = {64, 16, 2, 2};
    CUtensorMap tmXd = make_map(enc, d_in[3], 4, dXd, sXd, bXd, CU_TENSOR_MAP_SWIZZLE_128B, P256);
    const cuuint64_t dB[4] = {1024, 8, 4, 32}, sB[3] = {2048, 256 * 2048, 8 * 2048};
    const cuuint32_t bB4[4] = {64, 8, 2, 4};
    CUtensorMap tmBre = make_map(enc, d_in[6], 4, dB, sB, bB4, CU_TENSOR_MAP_SWIZZLE_128B, P256);
    CUtensorMap tmBim = make_map(enc, d_in[7], 4, dB, sB, bB4, CU_TENSOR_MAP_SWIZZLE_128B, P256);
    const cuuint64_t dC[5] = {1024, 2, 4, 2, 64}, sC[4] = {2048, 4 * 2048, 2 * 2048, 16 * 2048};
    const cuuint32_t bC[5] = {64, 2, 4, 2, 4};
    CUtensorMap tmCre = make_map(enc, d_in[8], 5, dC, sC, bC, CU_TENSOR_MAP_SWIZZLE_128B, P256);
    CUtensorMap tmCim = make_map(enc, d_in[9], 5, dC, sC, bC, CU_TENSOR_MAP_SWIZZLE_128B, P256);

    const cuuint64_t dU[2] = {8192, 256}, sU[1] = {16384};
    const cuuint32_t bU[2] = {64, 64};
    CUtensorMap tmUst = make_map(enc, pX, 2, dU, sU, bU, CU_TENSOR_MAP_SWIZZLE_128B, P0);
    const cuuint64_t dV[2] = {16384, 128}, sV[1] = {32768};
    const cuuint32_t bV[2] = {32, 128};
    CUtensorMap tmVst = make_map(enc, (uint8_t*)pX + (4 << 20), 2, dV, sV, bV, CU_TENSOR_MAP_SWIZZLE_NONE, P0);
    const cuuint64_t dF[2] = {512 * 1026 / 8, 4}, sF[1] = {512 * 1026};
    const cuuint32_t bF[2] = {WPITCH / 8, 4};
    CUtensorMap tmWr = make_map(enc, d_in[1], 2, dF, sF, bF, CU_TENSOR_MAP_SWIZZLE_NONE, P0, CU_TENSOR_MAP_DATA_TYPE_UINT64);
    CUtensorMap tmWi = make_map(enc, d_in[2], 2, dF, sF, bF, CU_TENSOR_MAP_SWIZZLE_NONE, P0, CU_TENSOR_MAP_DATA_TYPE_UINT64);

    const cuuint64_t dA[3] = {1024, 64, 32}, sA[2] = {32 * 2048, 2048};
    const cuuint32_t bA[3] = {32, 64, 1};
    CUtensorMap tmXa = make_map(enc, d_in[0], 3, dA, sA, bA, CU_TENSOR_MAP_SWIZZLE_64B, CU_TENSOR_MAP_L2_PROMOTION_L2_128B);

    Params p;
    p.wr = (const __nv_bfloat16*)d_in[1];
    p.wi = (const __nv_bfloat16*)d_in[2];
    p.lre = (const __nv_bfloat16*)d_in[4];
    p.lim = (const __nv_bfloat16*)d_in[5];
    p.ldt = (const __nv_bfloat16*)d_in[10];
    p.dsk = (const __nv_bfloat16*)d_in[11];
    p.out = (float*)d_out;
    int dev = 0, sms = 0;
    cudaGetDevice(&dev);
    cudaDeviceGetAttribute(&sms, cudaDevAttrMultiProcessorCount, dev);
    auto kernel = sms == 132 ? fused_kernel<true> : fused_kernel<false>;
    cudaFuncSetAttribute(kernel, cudaFuncAttributeMaxDynamicSharedMemorySize, SMEM_BYTES);
    kernel<<<132, 512, SMEM_BYTES>>>(tmX, tmBre, tmBim, tmCre, tmCim, tmXd, tmUst, tmVst, tmWr, tmWi, tmXa, p);
}
```

```cpp
#include <cuda_runtime.h>
#include <cuda.h>
#include <cuda_bf16.h>
#include <stdint.h>

#define NST 5
#define WPITCH 1056
#define OFF_P (NST * 32768)
#define OFF_F (OFF_P + 32768)
#define OFF_WD (OFF_F + 8192)
#define OFF_WM (OFF_WD + 8 * WPITCH)
#define OFF_BAR (OFF_F + 32768)
#define OFF_LAM (OFF_BAR + 432)
#define OFF_WSP (OFF_LAM + 2048)
#define OFF_PROF (OFF_WSP + 128)
#define SMEM_BYTES OFF_PROF
#define B_FULL 0
#define B_HL 40
#define B_EP 120
#define B_HR 128
#define B_XD 144
#define B_FG 160
#define B_WSP 168
#define B_WD 176
#define B_DONE 184
#define B_LD 192
#define B_RAW 200
#define B_LAM 208
#define B_IN 216
#define B_XIN 248
#define B_EMPTY 256
#define B_STG 320
#define B_WFREE 328
#define B_HOWN 336
#define B_STGU 368
#define B_P3M 384
#define B_EPOCH 416

#define XA_PACE 200
#define PACE_O 200
#define PACE_ON 2
#define TAB_T0 500
#define LAM_T0 1000
#define XA_N0 2
#define PACE_X 200
#define SKEW 4
#define SPIN_LIMIT (1u << 15)

__device__ __align__(1024) uint8_t g_X[8 << 20];
__device__ __align__(1024) uint8_t g_H[8 << 20];
__device__ __align__(1024) uint4 g_carry[16 * 512];
__device__ __align__(128) unsigned g_cnt[128];
__device__ __align__(128) unsigned g_epoch[132 * 8];

#define STAMP(i) do { } while (0)
#define STAMPO(i, o) do { } while (0)
#define STAMPW(a, b) do { } while (0)
#define STAMPX(a, b) do { } while (0)
#define STAMP5(i) do { } while (0)
#define STAMP3(i) do { } while (0)

#define TAB_FG 0
#define TAB_G 8192
#define TAB_F1 40960
#define TAB_T 49152
#define TAB_SP 57344
#define TAB_TW1 73728
#define TAB_TW3 75776
#define TAB_PC 83968
__device__ __align__(1024) const uint32_t g_tab[21248] = {
0x80003d80,0x80003d80,0x80003d80,0x80003d80,0x80003d80,0x80003d80,0x80003d80,0x80003d80,0x80003d80,0x80003d80,0x80003d80,0x80003d80,0x80003d80,0x80003d80,0x80003d80,0x80003d80,
0x80003d80,0x80003d80,0x80003d80,0x80003d80,0x80003d80,0x80003d80,0x80003d80,0x80003d80,0x80003d80,0x80003d80,0x80003d80,0x80003d80,0x80003d80,0x80003d80,0x80003d80,0x80003d80,
0x3d353d35,0x3d35bd35,0xbd35bd35,0xbd353d35,0x80003d80,0x3d800000,0x8000bd80,0xbd800000,0x3d353d35,0x3d35bd35,0xbd35bd35,0xbd353d35,0x80003d80,0x3d800000,0x8000bd80,0xbd800000,
0x3d353d35,0x3d35bd35,0xbd35bd35,0xbd353d35,0x80003d80,0x3d800000,0x8000bd80,0xbd800000,0x3d353d35,0x3d35bd35,0xbd35bd35,0xbd353d35,0x80003d80,0x3d800000,0x8000bd80,0xbd800000,
0x3d800000,0x3d6dbcc4,0x3d35bd35,0x3cc4bd6d,0x3d7bbc48,0x3d55bd0e,0x3d0ebd55,0x3c48bd7b,0x80003d80,0x3cc43d6d,0x3d353d35,0x3d6d3cc4,0x3c483d7b,0x3d0e3d55,0x3d553d0e,0x3d7b3c48,
0xbd800000,0xbd6d3cc4,0xbd353d35,0xbcc43d6d,0xbd7b3c48,0xbd553d0e,0xbd0e3d55,0xbc483d7b,0x8000bd80,0xbcc4bd6d,0xbd35bd35,0xbd6dbcc4,0xbc48bd7b,0xbd0ebd55,0xbd55bd0e,0xbd7bbc48,
0x3d0ebd55,0xbd7bbc48,0x3c483d7b,0x3d55bd0e,0x3d800000,0xbcc4bd6d,0xbd353d35,0x3d6d3cc4,0x3d553d0e,0x3c48bd7b,0xbd7b3c48,0x3d0e3d55,0x80003d80,0x3d6dbcc4,0xbd35bd35,0xbcc43d6d,
0xbd0e3d55,0x3d7b3c48,0xbc48bd7b,0xbd553d0e,0xbd800000,0x3cc43d6d,0x3d35bd35,0xbd6dbcc4,0xbd55bd0e,0xbc483d7b,0x3d7bbc48,0xbd0ebd55,0x8000bd80,0xbd6d3cc4,0x3d353d35,0x3cc4bd6d,
0x80003d80,0x3d353d35,0x3d800000,0x3d35bd35,0x3cc43d6d,0x3d6d3cc4,0x3d6dbcc4,0x3cc4bd6d,0x8000bd80,0xbd35bd35,0xbd800000,0xbd353d35,0xbcc4bd6d,0xbd6dbcc4,0xbd6d3cc4,0xbcc43d6d,
0x80003d80,0x3d353d35,0x3d800000,0x3d35bd35,0x3cc43d6d,0x3d6d3cc4,0x3d6dbcc4,0x3cc4bd6d,0x8000bd80,0xbd35bd35,0xbd800000,0xbd353d35,0xbcc4bd6d,0xbd6dbcc4,0xbd6d3cc4,0xbcc43d6d,
0x3d6d3cc4,0xbcc4bd6d,0xbcc43d6d,0x3d6dbcc4,0x80003d80,0x3d35bd35,0xbd800000,0x3d353d35,0xbd6dbcc4,0x3cc43d6d,0x3cc4bd6d,0xbd6d3cc4,0x8000bd80,0xbd353d35,0x3d800000,0xbd35bd35,
0x3d6d3cc4,0xbcc4bd6d,0xbcc43d6d,0x3d6dbcc4,0x80003d80,0x3d35bd35,0xbd800000,0x3d353d35,0xbd6dbcc4,0x3cc43d6d,0x3cc4bd6d,0xbd6d3cc4,0x8000bd80,0xbd353d35,0x3d800000,0xbd35bd35,
0x3d800000,0x3cc4bd6d,0xbd35bd35,0xbd6d3cc4,0x3d55bd0e,0xbc48bd7b,0xbd7bbc48,0xbd0e3d55,0x8000bd80,0xbd6dbcc4,0xbd353d35,0x3cc43d6d,0xbd0ebd55,0xbd7b3c48,0xbc483d7b,0x3d553d0e,
0xbd800000,0xbcc43d6d,0x3d353d35,0x3d6dbcc4,0xbd553d0e,0x3c483d7b,0x3d7b3c48,0x3d0ebd55,0x80003d80,0x3d6d3cc4,0x3d35bd35,0xbcc4bd6d,0x3d0e3d55,0x3d7bbc48,0x3c48bd7b,0xbd55bd0e,
0x3c48bd7b,0xbd0e3d55,0x3d55bd0e,0xbd7b3c48,0x3d800000,0xbd6dbcc4,0x3d353d35,0xbcc4bd6d,0xbd7bbc48,0x3d553d0e,0xbd0ebd55,0x3c483d7b,0x8000bd80,0xbcc43d6d,0x3d35bd35,0xbd6d3cc4,
0xbc483d7b,0x3d0ebd55,0xbd553d0e,0x3d7bbc48,0xbd800000,0x3d6d3cc4,0xbd35bd35,0x3cc43d6d,0x3d7b3c48,0xbd55bd0e,0x3d0e3d55,0xbc48bd7b,0x80003d80,0x3cc4bd6d,0xbd353d35,0x3d6dbcc4,
0x3d800000,0x3d800000,0x3d800000,0x3d800000,0x3d800000,0x3d800000,0x3d800000,0x3d800000,0x3d800000,0x3d800000,0x3d800000,0x3d800000,0x3d800000,0x3d800000,0x3d800000,0x3d800000,
0x3d800000,0x3d800000,0x3d800000,0x3d800000,0x3d800000,0x3d800000,0x3d800000,0x3d800000,0x3d800000,0x3d800000,0x3d800000,0x3d800000,0x3d800000,0x3d800000,0x3d800000,0x3d800000,
0x3d35bd35,0xbd35bd35,0xbd353d35,0x3d353d35,0x3d800000,0xbd80,0xbd800000,0x3d80,0x3d35bd35,0xbd35bd35,0xbd353d35,0x3d353d35,0x3d800000,0xbd80,0xbd800000,0x3d80,
0x3d35bd35,0xbd35bd35,0xbd353d35,0x3d353d35,0x3d800000,0xbd80,0xbd800000,0x3d80,0x3d35bd35,0xbd35bd35,0xbd353d35,0x3d353d35,0x3d800000,0xbd80,0xbd800000,0x3d80,
0xbd80,0xbcc4bd6d,0xbd35bd35,0xbd6dbcc4,0xbc48bd7b,0xbd0ebd55,0xbd55bd0e,0xbd7bbc48,0x3d800000,0x3d6dbcc4,0x3d35bd35,0x3cc4bd6d,0x3d7bbc48,0x3d55bd0e,0x3d0ebd55,0x3c48bd7b,
0x3d80,0x3cc43d6d,0x3d353d35,0x3d6d3cc4,0x3c483d7b,0x3d0e3d55,0x3d553d0e,0x3d7b3c48,0xbd800000,0xbd6d3cc4,0xbd353d35,0xbcc43d6d,0xbd7b3c48,0xbd553d0e,0xbd0e3d55,0xbc483d7b,
0xbd55bd0e,0xbc483d7b,0x3d7bbc48,0xbd0ebd55,0xbd80,0xbd6d3cc4,0x3d353d35,0x3cc4bd6d,0x3d0ebd55,0xbd7bbc48,0x3c483d7b,0x3d55bd0e,0x3d800000,0xbcc4bd6d,0xbd353d35,0x3d6d3cc4,
0x3d553d0e,0x3c48bd7b,0xbd7b3c48,0x3d0e3d55,0x3d80,0x3d6dbcc4,0xbd35bd35,0xbcc43d6d,0xbd0e3d55,0x3d7b3c48,0xbc48bd7b,0xbd553d0e,0xbd800000,0x3cc43d6d,0x3d35bd35,0xbd6dbcc4,
0x3d800000,0x3d35bd35,0xbd80,0xbd35bd35,0x3d6dbcc4,0x3cc4bd6d,0xbcc4bd6d,0xbd6dbcc4,0xbd800000,0xbd353d35,0x3d80,0x3d353d35,0xbd6d3cc4,0xbcc43d6d,0x3cc43d6d,0x3d6d3cc4,
0x3d800000,0x3d35bd35,0xbd80,0xbd35bd35,0x3d6dbcc4,0x3cc4bd6d,0xbcc4bd6d,0xbd6dbcc4,0xbd800000,0xbd353d35,0x3d80,0x3d353d35,0xbd6d3cc4,0xbcc43d6d,0x3cc43d6d,0x3d6d3cc4,
0x3cc4bd6d,0xbd6d3cc4,0x3d6d3cc4,0xbcc4bd6d,0x3d800000,0xbd35bd35,0x3d80,0x3d35bd35,0xbcc43d6d,0x3d6dbcc4,0xbd6dbcc4,0x3cc43d6d,0xbd800000,0x3d353d35,0xbd80,0xbd353d35,
0x3cc4bd6d,0xbd6d3cc4,0x3d6d3cc4,0xbcc4bd6d,0x3d800000,0xbd35bd35,0x3d80,0x3d35bd35,0xbcc43d6d,0x3d6dbcc4,0xbd6dbcc4,0x3cc43d6d,0xbd800000,0x3d353d35,0xbd80,0xbd353d35,
0xbd80,0xbd6dbcc4,0xbd353d35,0x3cc43d6d,0xbd0ebd55,0xbd7b3c48,0xbc483d7b,0x3d553d0e,0xbd800000,0xbcc43d6d,0x3d353d35,0x3d6dbcc4,0xbd553d0e,0x3c483d7b,0x3d7b3c48,0x3d0ebd55,
0x3d80,0x3d6d3cc4,0x3d35bd35,0xbcc4bd6d,0x3d0e3d55,0x3d7bbc48,0x3c48bd7b,0xbd55bd0e,0x3d800000,0x3cc4bd6d,0xbd35bd35,0xbd6d3cc4,0x3d55bd0e,0xbc48bd7b,0xbd7bbc48,0xbd0e3d55,
0xbd7bbc48,0x3d553d0e,0xbd0ebd55,0x3c483d7b,0xbd80,0xbcc43d6d,0x3d35bd35,0xbd6d3cc4,0xbc483d7b,0x3d0ebd55,0xbd553d0e,0x3d7bbc48,0xbd800000,0x3d6d3cc4,0xbd35bd35,0x3cc43d6d,
0x3d7b3c48,0xbd55bd0e,0x3d0e3d55,0xbc48bd7b,0x3d80,0x3cc4bd6d,0xbd353d35,0x3d6dbcc4,0x3c48bd7b,0xbd0e3d55,0x3d55bd0e,0xbd7b3c48,0x3d800000,0xbd6dbcc4,0x3d353d35,0xbcc4bd6d,
0x80003d80,0x8000bd80,0x80003d80,0x8000bd80,0x3d800000,0xbd800000,0x3d800000,0xbd800000,0x80003d80,0x8000bd80,0x80003d80,0x8000bd80,0x3d800000,0xbd800000,0x3d800000,0xbd800000,
0x80003d80,0x8000bd80,0x80003d80,0x8000bd80,0x3d800000,0xbd800000,0x3d800000,0xbd800000,0x80003d80,0x8000bd80,0x80003d80,0x8000bd80,0x3d800000,0xbd800000,0x3d800000,0xbd800000,
0x3d35bd35,0x3d353d35,0xbd353d35,0xbd35bd35,0x80003d80,0xbd800000,0x8000bd80,0x3d800000,0x3d35bd35,0x3d353d35,0xbd353d35,0xbd35bd35,0x80003d80,0xbd800000,0x8000bd80,0x3d800000,
0x3d35bd35,0x3d353d35,0xbd353d35,0xbd35bd35,0x80003d80,0xbd800000,0x8000bd80,0x3d800000,0x3d35bd35,0x3d353d35,0xbd353d35,0xbd35bd35,0x80003d80,0xbd800000,0x8000bd80,0x3d800000,
0x3d800000,0xbd6d3cc4,0x3d35bd35,0xbcc43d6d,0xbc48bd7b,0x3d0e3d55,0xbd55bd0e,0x3d7b3c48,0x80003d80,0xbcc4bd6d,0x3d353d35,0xbd6dbcc4,0x3d7bbc48,0xbd553d0e,0x3d0ebd55,0xbc483d7b,
0xbd800000,0x3d6dbcc4,0xbd353d35,0x3cc4bd6d,0x3c483d7b,0xbd0ebd55,0x3d553d0e,0xbd7bbc48,0x8000bd80,0x3cc43d6d,0xbd35bd35,0x3d6d3cc4,0xbd7b3c48,0x3d55bd0e,0xbd0e3d55,0x3c48bd7b,
0xbd55bd0e,0x3c48bd7b,0x3d7bbc48,0x3d0e3d55,0x3d800000,0x3cc43d6d,0xbd353d35,0xbd6dbcc4,0x3d0ebd55,0x3d7b3c48,0x3c483d7b,0xbd553d0e,0x80003d80,0xbd6d3cc4,0xbd35bd35,0x3cc4bd6d,
0x3d553d0e,0xbc483d7b,0xbd7b3c48,0xbd0ebd55,0xbd800000,0xbcc4bd6d,0x3d35bd35,0x3d6d3cc4,0xbd0e3d55,0xbd7bbc48,0xbc48bd7b,0x3d55bd0e,0x8000bd80,0x3d6dbcc4,0x3d353d35,0xbcc43d6d,
0x80003d80,0xbd35bd35,0x3d800000,0xbd353d35,0x3d6dbcc4,0xbcc43d6d,0xbcc4bd6d,0x3d6d3cc4,0x8000bd80,0x3d353d35,0xbd800000,0x3d35bd35,0xbd6d3cc4,0x3cc4bd6d,0x3cc43d6d,0xbd6dbcc4,
0x80003d80,0xbd35bd35,0x3d800000,0xbd353d35,0x3d6dbcc4,0xbcc43d6d,0xbcc4bd6d,0x3d6d3cc4,0x8000bd80,0x3d353d35,0xbd800000,0x3d35bd35,0xbd6d3cc4,0x3cc4bd6d,0x3cc43d6d,0xbd6dbcc4,
0x3cc4bd6d,0x3d6dbcc4,0x3d6d3cc4,0x3cc43d6d,0x80003d80,0xbd353d35,0xbd800000,0xbd35bd35,0xbcc43d6d,0xbd6d3cc4,0xbd6dbcc4,0xbcc4bd6d,0x8000bd80,0x3d35bd35,0x3d800000,0x3d353d35,
0x3cc4bd6d,0x3d6dbcc4,0x3d6d3cc4,0x3cc43d6d,0x80003d80,0xbd353d35,0xbd800000,0xbd35bd35,0xbcc43d6d,0xbd6d3cc4,0xbd6dbcc4,0xbcc4bd6d,0x8000bd80,0x3d35bd35,0x3d800000,0x3d353d35,
0x3d800000,0xbcc43d6d,0xbd35bd35,0x3d6dbcc4,0xbd0ebd55,0x3d7bbc48,0xbc483d7b,0xbd55bd0e,0x8000bd80,0x3d6d3cc4,0xbd353d35,0xbcc4bd6d,0xbd553d0e,0xbc48bd7b,0x3d7b3c48,0xbd0e3d55,
0xbd800000,0x3cc4bd6d,0x3d353d35,0xbd6d3cc4,0x3d0e3d55,0xbd7b3c48,0x3c48bd7b,0x3d553d0e,0x80003d80,0xbd6dbcc4,0x3d35bd35,0x3cc43d6d,0x3d55bd0e,0x3c483d7b,0xbd7bbc48,0x3d0ebd55,
0xbd7bbc48,0xbd55bd0e,0xbd0ebd55,0xbc48bd7b,0x3d800000,0x3d6d3cc4,0x3d353d35,0x3cc43d6d,0xbc483d7b,0xbd0e3d55,0xbd553d0e,0xbd7b3c48,0x8000bd80,0x3cc4bd6d,0x3d35bd35,0x3d6dbcc4,
0x3d7b3c48,0x3d553d0e,0x3d0e3d55,0x3c483d7b,0xbd800000,0xbd6dbcc4,0xbd35bd35,0xbcc4bd6d,0x3c48bd7b,0x3d0ebd55,0x3d55bd0e,0x3d7bbc48,0x80003d80,0xbcc43d6d,0xbd353d35,0xbd6d3cc4,
0x3d800000,0xbd800000,0x3d800000,0xbd800000,0xbd80,0x3d80,0xbd80,0x3d80,0x3d800000,0xbd800000,0x3d800000,0xbd800000,0xbd80,0x3d80,0xbd80,0x3d80,
0x3d800000,0xbd800000,0x3d800000,0xbd800000,0xbd80,0x3d80,0xbd80,0x3d80,0x3d800000,0xbd800000,0x3d800000,0xbd800000,0xbd80,0x3d80,0xbd80,0x3d80,
0xbd35bd35,0x3d35bd35,0x3d353d35,0xbd353d35,0x3d800000,0x3d80,0xbd800000,0xbd80,0xbd35bd35,0x3d35bd35,0x3d353d35,0xbd353d35,0x3d800000,0x3d80,0xbd800000,0xbd80,
0xbd35bd35,0x3d35bd35,0x3d353d35,0xbd353d35,0x3d800000,0x3d80,0xbd800000,0xbd80,0xbd35bd35,0x3d35bd35,0x3d353d35,0xbd353d35,0x3d800000,0x3d80,0xbd800000,0xbd80,
0xbd80,0x3cc43d6d,0xbd35bd35,0x3d6d3cc4,0xbd7b3c48,0x3d55bd0e,0xbd0e3d55,0x3c48bd7b,0x3d800000,0xbd6d3cc4,0x3d35bd35,0xbcc43d6d,0xbc48bd7b,0x3d0e3d55,0xbd55bd0e,0x3d7b3c48,
0x3d80,0xbcc4bd6d,0x3d353d35,0xbd6dbcc4,0x3d7bbc48,0xbd553d0e,0x3d0ebd55,0xbc483d7b,0xbd800000,0x3d6dbcc4,0xbd353d35,0x3cc4bd6d,0x3c483d7b,0xbd0ebd55,0x3d553d0e,0xbd7bbc48,
0xbd0e3d55,0xbd7bbc48,0xbc48bd7b,0x3d55bd0e,0xbd80,0x3d6dbcc4,0x3d353d35,0xbcc43d6d,0xbd55bd0e,0x3c48bd7b,0x3d7bbc48,0x3d0e3d55,0x3d800000,0x3cc43d6d,0xbd353d35,0xbd6dbcc4,
0x3d0ebd55,0x3d7b3c48,0x3c483d7b,0xbd553d0e,0x3d80,0xbd6d3cc4,0xbd35bd35,0x3cc4bd6d,0x3d553d0e,0xbc483d7b,0xbd7b3c48,0xbd0ebd55,0xbd800000,0xbcc4bd6d,0x3d35bd35,0x3d6d3cc4,
0x3d800000,0xbd353d35,0xbd80,0x3d353d35,0xbcc4bd6d,0x3d6d3cc4,0xbd6d3cc4,0x3cc4bd6d,0xbd800000,0x3d35bd35,0x3d80,0xbd35bd35,0x3cc43d6d,0xbd6dbcc4,0x3d6dbcc4,0xbcc43d6d,
0x3d800000,0xbd353d35,0xbd80,0x3d353d35,0xbcc4bd6d,0x3d6d3cc4,0xbd6d3cc4,0x3cc4bd6d,0xbd800000,0x3d35bd35,0x3d80,0xbd35bd35,0x3cc43d6d,0xbd6dbcc4,0x3d6dbcc4,0xbcc43d6d,
0xbd6dbcc4,0xbcc4bd6d,0x3cc4bd6d,0x3d6dbcc4,0x3d800000,0x3d353d35,0x3d80,0xbd353d35,0x3d6d3cc4,0x3cc43d6d,0xbcc43d6d,0xbd6d3cc4,0xbd800000,0xbd35bd35,0xbd80,0x3d35bd35,
0xbd6dbcc4,0xbcc4bd6d,0x3cc4bd6d,0x3d6dbcc4,0x3d800000,0x3d353d35,0x3d80,0xbd353d35,0x3d6d3cc4,0x3cc43d6d,0xbcc43d6d,0xbd6d3cc4,0xbd800000,0xbd35bd35,0xbd80,0x3d35bd35,
0xbd80,0x3d6d3cc4,0xbd353d35,0xbcc4bd6d,0xbd553d0e,0xbc48bd7b,0x3d7b3c48,0xbd0e3d55,0xbd800000,0x3cc4bd6d,0x3d353d35,0xbd6d3cc4,0x3d0e3d55,0xbd7b3c48,0x3c48bd7b,0x3d553d0e,
0x3d80,0xbd6dbcc4,0x3d35bd35,0x3cc43d6d,0x3d55bd0e,0x3c483d7b,0xbd7bbc48,0x3d0ebd55,0x3d800000,0xbcc43d6d,0xbd35bd35,0x3d6dbcc4,0xbd0ebd55,0x3d7bbc48,0xbc483d7b,0xbd55bd0e,
0xbc483d7b,0xbd0e3d55,0xbd553d0e,0xbd7b3c48,0xbd80,0x3cc4bd6d,0x3d35bd35,0x3d6dbcc4,0x3d7b3c48,0x3d553d0e,0x3d0e3d55,0x3c483d7b,0xbd800000,0xbd6dbcc4,0xbd35bd35,0xbcc4bd6d,
0x3c48bd7b,0x3d0ebd55,0x3d55bd0e,0x3d7bbc48,0x3d80,0xbcc43d6d,0xbd353d35,0xbd6d3cc4,0xbd7bbc48,0xbd55bd0e,0xbd0ebd55,0xbc48bd7b,0x3d800000,0x3d6d3cc4,0x3d353d35,0x3cc43d6d,
0x80003d80,0x80003d80,0x80003d80,0x80003d80,0x8000bd80,0x8000bd80,0x8000bd80,0x8000bd80,0x80003d80,0x80003d80,0x80003d80,0x80003d80,0x8000bd80,0x8000bd80,0x8000bd80,0x8000bd80,
0x80003d80,0x80003d80,0x80003d80,0x80003d80,0x8000bd80,0x8000bd80,0x8000bd80,0x8000bd80,0x80003d80,0x80003d80,0x80003d80,0x80003d80,0x8000bd80,0x8000bd80,0x8000bd80,0x8000bd80,
0xbd35bd35,0xbd353d35,0x3d353d35,0x3d35bd35,0x80003d80,0x3d800000,0x8000bd80,0xbd800000,0xbd35bd35,0xbd353d35,0x3d353d35,0x3d35bd35,0x80003d80,0x3d800000,0x8000bd80,0xbd800000,
0xbd35bd35,0xbd353d35,0x3d353d35,0x3d35bd35,0x80003d80,0x3d800000,0x8000bd80,0xbd800000,0xbd35bd35,0xbd353d35,0x3d353d35,0x3d35bd35,0x80003d80,0x3d800000,0x8000bd80,0xbd800000,
0x3d800000,0x3d6dbcc4,0x3d35bd35,0x3cc4bd6d,0xbd7b3c48,0xbd553d0e,0xbd0e3d55,0xbc483d7b,0x80003d80,0x3cc43d6d,0x3d353d35,0x3d6d3cc4,0xbc48bd7b,0xbd0ebd55,0xbd55bd0e,0xbd7bbc48,
0xbd800000,0xbd6d3cc4,0xbd353d35,0xbcc43d6d,0x3d7bbc48,0x3d55bd0e,0x3d0ebd55,0x3c48bd7b,0x8000bd80,0xbcc4bd6d,0xbd35bd35,0xbd6dbcc4,0x3c483d7b,0x3d0e3d55,0x3d553d0e,0x3d7b3c48,
0xbd0e3d55,0x3d7b3c48,0xbc48bd7b,0xbd553d0e,0x3d800000,0xbcc4bd6d,0xbd353d35,0x3d6d3cc4,0xbd55bd0e,0xbc483d7b,0x3d7bbc48,0xbd0ebd55,0x80003d80,0x3d6dbcc4,0xbd35bd35,0xbcc43d6d,
0x3d0ebd55,0xbd7bbc48,0x3c483d7b,0x3d55bd0e,0xbd800000,0x3cc43d6d,0x3d35bd35,0xbd6dbcc4,0x3d553d0e,0x3c48bd7b,0xbd7b3c48,0x3d0e3d55,0x8000bd80,0xbd6d3cc4,0x3d353d35,0x3cc4bd6d,
0x80003d80,0x3d353d35,0x3d800000,0x3d35bd35,0xbcc4bd6d,0xbd6dbcc4,0xbd6d3cc4,0xbcc43d6d,0x8000bd80,0xbd35bd35,0xbd800000,0xbd353d35,0x3cc43d6d,0x3d6d3cc4,0x3d6dbcc4,0x3cc4bd6d,
0x80003d80,0x3d353d35,0x3d800000,0x3d35bd35,0xbcc4bd6d,0xbd6dbcc4,0xbd6d3cc4,0xbcc43d6d,0x8000bd80,0xbd35bd35,0xbd800000,0xbd353d35,0x3cc43d6d,0x3d6d3cc4,0x3d6dbcc4,0x3cc4bd6d,
0xbd6dbcc4,0x3cc43d6d,0x3cc4bd6d,0xbd6d3cc4,0x80003d80,0x3d35bd35,0xbd800000,0x3d353d35,0x3d6d3cc4,0xbcc4bd6d,0xbcc43d6d,0x3d6dbcc4,0x8000bd80,0xbd353d35,0x3d800000,0xbd35bd35,
0xbd6dbcc4,0x3cc43d6d,0x3cc4bd6d,0xbd6d3cc4,0x80003d80,0x3d35bd35,0xbd800000,0x3d353d35,0x3d6d3cc4,0xbcc4bd6d,0xbcc43d6d,0x3d6dbcc4,0x8000bd80,0xbd353d35,0x3d800000,0xbd35bd35,
0x3d800000,0x3cc4bd6d,0xbd35bd35,0xbd6d3cc4,0xbd553d0e,0x3c483d7b,0x3d7b3c48,0x3d0ebd55,0x8000bd80,0xbd6dbcc4,0xbd353d35,0x3cc43d6d,0x3d0e3d55,0x3d7bbc48,0x3c48bd7b,0xbd55bd0e,
0xbd800000,0xbcc43d6d,0x3d353d35,0x3d6dbcc4,0x3d55bd0e,0xbc48bd7b,0xbd7bbc48,0xbd0e3d55,0x80003d80,0x3d6d3cc4,0x3d35bd35,0xbcc4bd6d,0xbd0ebd55,0xbd7b3c48,0xbc483d7b,0x3d553d0e,
0xbc483d7b,0x3d0ebd55,0xbd553d0e,0x3d7bbc48,0x3d800000,0xbd6dbcc4,0x3d353d35,0xbcc4bd6d,0x3d7b3c48,0xbd55bd0e,0x3d0e3d55,0xbc48bd7b,0x8000bd80,0xbcc43d6d,0x3d35bd35,0xbd6d3cc4,
0x3c48bd7b,0xbd0e3d55,0x3d55bd0e,0xbd7b3c48,0xbd800000,0x3d6d3cc4,0xbd35bd35,0x3cc43d6d,0xbd7bbc48,0x3d553d0e,0xbd0ebd55,0x3c483d7b,0x80003d80,0x3cc4bd6d,0xbd353d35,0x3d6dbcc4,
0x3d800000,0x3d800000,0x3d800000,0x3d800000,0xbd800000,0xbd800000,0xbd800000,0xbd800000,0x3d800000,0x3d800000,0x3d800000,0x3d800000,0xbd800000,0xbd800000,0xbd800000,0xbd800000,
0x3d800000,0x3d800000,0x3d800000,0x3d800000,0xbd800000,0xbd800000,0xbd800000,0xbd800000,0x3d800000,0x3d800000,0x3d800000,0x3d800000,0xbd800000,0xbd800000,0xbd800000,0xbd800000,
0xbd353d35,0x3d353d35,0x3d35bd35,0xbd35bd35,0x3d800000,0xbd80,0xbd800000,0x3d80,0xbd353d35,0x3d353d35,0x3d35bd35,0xbd35bd35,0x3d800000,0xbd80,0xbd800000,0x3d80,
0xbd353d35,0x3d353d35,0x3d35bd35,0xbd35bd35,0x3d800000,0xbd80,0xbd800000,0x3d80,0xbd353d35,0x3d353d35,0x3d35bd35,0xbd35bd35,0x3d800000,0xbd80,0xbd800000,0x3d80,
0xbd80,0xbcc4bd6d,0xbd35bd35,0xbd6dbcc4,0x3c483d7b,0x3d0e3d55,0x3d553d0e,0x3d7b3c48,0x3d800000,0x3d6dbcc4,0x3d35bd35,0x3cc4bd6d,0xbd7b3c48,0xbd553d0e,0xbd0e3d55,0xbc483d7b,
0x3d80,0x3cc43d6d,0x3d353d35,0x3d6d3cc4,0xbc48bd7b,0xbd0ebd55,0xbd55bd0e,0xbd7bbc48,0xbd800000,0xbd6d3cc4,0xbd353d35,0xbcc43d6d,0x3d7bbc48,0x3d55bd0e,0x3d0ebd55,0x3c48bd7b,
0x3d553d0e,0x3c48bd7b,0xbd7b3c48,0x3d0e3d55,0xbd80,0xbd6d3cc4,0x3d353d35,0x3cc4bd6d,0xbd0e3d55,0x3d7b3c48,0xbc48bd7b,0xbd553d0e,0x3d800000,0xbcc4bd6d,0xbd353d35,0x3d6d3cc4,
0xbd55bd0e,0xbc483d7b,0x3d7bbc48,0xbd0ebd55,0x3d80,0x3d6dbcc4,0xbd35bd35,0xbcc43d6d,0x3d0ebd55,0xbd7bbc48,0x3c483d7b,0x3d55bd0e,0xbd800000,0x3cc43d6d,0x3d35bd35,0xbd6dbcc4,
0x3d800000,0x3d35bd35,0xbd80,0xbd35bd35,0xbd6d3cc4,0xbcc43d6d,0x3cc43d6d,0x3d6d3cc4,0xbd800000,0xbd353d35,0x3d80,0x3d353d35,0x3d6dbcc4,0x3cc4bd6d,0xbcc4bd6d,0xbd6dbcc4,
0x3d800000,0x3d35bd35,0xbd80,0xbd35bd35,0xbd6d3cc4,0xbcc43d6d,0x3cc43d6d,0x3d6d3cc4,0xbd800000,0xbd353d35,0x3d80,0x3d353d35,0x3d6dbcc4,0x3cc4bd6d,0xbcc4bd6d,0xbd6dbcc4,
0xbcc43d6d,0x3d6dbcc4,0xbd6dbcc4,0x3cc43d6d,0x3d800000,0xbd35bd35,0x3d80,0x3d35bd35,0x3cc4bd6d,0xbd6d3cc4,0x3d6d3cc4,0xbcc4bd6d,0xbd800000,0x3d353d35,0xbd80,0xbd353d35,
0xbcc43d6d,0x3d6dbcc4,0xbd6dbcc4,0x3cc43d6d,0x3d800000,0xbd35bd35,0x3d80,0x3d35bd35,0x3cc4bd6d,0xbd6d3cc4,0x3d6d3cc4,0xbcc4bd6d,0xbd800000,0x3d353d35,0xbd80,0xbd353d35,
0xbd80,0xbd6dbcc4,0xbd353d35,0x3cc43d6d,0x3d0e3d55,0x3d7bbc48,0x3c48bd7b,0xbd55bd0e,0xbd800000,0xbcc43d6d,0x3d353d35,0x3d6dbcc4,0x3d55bd0e,0xbc48bd7b,0xbd7bbc48,0xbd0e3d55,
0x3d80,0x3d6d3cc4,0x3d35bd35,0xbcc4bd6d,0xbd0ebd55,0xbd7b3c48,0xbc483d7b,0x3d553d0e,0x3d800000,0x3cc4bd6d,0xbd35bd35,0xbd6d3cc4,0xbd553d0e,0x3c483d7b,0x3d7b3c48,0x3d0ebd55,
0x3d7b3c48,0xbd55bd0e,0x3d0e3d55,0xbc48bd7b,0xbd80,0xbcc43d6d,0x3d35bd35,0xbd6d3cc4,0x3c48bd7b,0xbd0e3d55,0x3d55bd0e,0xbd7b3c48,0xbd800000,0x3d6d3cc4,0xbd35bd35,0x3cc43d6d,
0xbd7bbc48,0x3d553d0e,0xbd0ebd55,0x3c483d7b,0x3d80,0x3cc4bd6d,0xbd353d35,0x3d6dbcc4,0xbc483d7b,0x3d0ebd55,0xbd553d0e,0x3d7bbc48,0x3d800000,0xbd6dbcc4,0x3d353d35,0xbcc4bd6d,
0x80003d80,0x8000bd80,0x80003d80,0x8000bd80,0xbd800000,0x3d800000,0xbd800000,0x3d800000,0x80003d80,0x8000bd80,0x80003d80,0x8000bd80,0xbd800000,0x3d800000,0xbd800000,0x3d800000,
0x80003d80,0x8000bd80,0x80003d80,0x8000bd80,0xbd800000,0x3d800000,0xbd800000,0x3d800000,0x80003d80,0x8000bd80,0x80003d80,0x8000bd80,0xbd800000,0x3d800000,0xbd800000,0x3d800000,
0xbd353d35,0xbd35bd35,0x3d35bd35,0x3d353d35,0x80003d80,0xbd800000,0x8000bd80,0x3d800000,0xbd353d35,0xbd35bd35,0x3d35bd35,0x3d353d35,0x80003d80,0xbd800000,0x8000bd80,0x3d800000,
0xbd353d35,0xbd35bd35,0x3d35bd35,0x3d353d35,0x80003d80,0xbd800000,0x8000bd80,0x3d800000,0xbd353d35,0xbd35bd35,0x3d35bd35,0x3d353d35,0x80003d80,0xbd800000,0x8000bd80,0x3d800000,
0x3d800000,0xbd6d3cc4,0x3d35bd35,0xbcc43d6d,0x3c483d7b,0xbd0ebd55,0x3d553d0e,0xbd7bbc48,0x80003d80,0xbcc4bd6d,0x3d353d35,0xbd6dbcc4,0xbd7b3c48,0x3d55bd0e,0xbd0e3d55,0x3c48bd7b,
0xbd800000,0x3d6dbcc4,0xbd353d35,0x3cc4bd6d,0xbc48bd7b,0x3d0e3d55,0xbd55bd0e,0x3d7b3c48,0x8000bd80,0x3cc43d6d,0xbd35bd35,0x3d6d3cc4,0x3d7bbc48,0xbd553d0e,0x3d0ebd55,0xbc483d7b,
0x3d553d0e,0xbc483d7b,0xbd7b3c48,0xbd0ebd55,0x3d800000,0x3cc43d6d,0xbd353d35,0xbd6dbcc4,0xbd0e3d55,0xbd7bbc48,0xbc48bd7b,0x3d55bd0e,0x80003d80,0xbd6d3cc4,0xbd35bd35,0x3cc4bd6d,
0xbd55bd0e,0x3c48bd7b,0x3d7bbc48,0x3d0e3d55,0xbd800000,0xbcc4bd6d,0x3d35bd35,0x3d6d3cc4,0x3d0ebd55,0x3d7b3c48,0x3c483d7b,0xbd553d0e,0x8000bd80,0x3d6dbcc4,0x3d353d35,0xbcc43d6d,
0x80003d80,0xbd35bd35,0x3d800000,0xbd353d35,0xbd6d3cc4,0x3cc4bd6d,0x3cc43d6d,0xbd6dbcc4,0x8000bd80,0x3d353d35,0xbd800000,0x3d35bd35,0x3d6dbcc4,0xbcc43d6d,0xbcc4bd6d,0x3d6d3cc4,
0x80003d80,0xbd35bd35,0x3d800000,0xbd353d35,0xbd6d3cc4,0x3cc4bd6d,0x3cc43d6d,0xbd6dbcc4,0x8000bd80,0x3d353d35,0xbd800000,0x3d35bd35,0x3d6dbcc4,0xbcc43d6d,0xbcc4bd6d,0x3d6d3cc4,
0xbcc43d6d,0xbd6d3cc4,0xbd6dbcc4,0xbcc4bd6d,0x80003d80,0xbd353d35,0xbd800000,0xbd35bd35,0x3cc4bd6d,0x3d6dbcc4,0x3d6d3cc4,0x3cc43d6d,0x8000bd80,0x3d35bd35,0x3d800000,0x3d353d35,
0xbcc43d6d,0xbd6d3cc4,0xbd6dbcc4,0xbcc4bd6d,0x80003d80,0xbd353d35,0xbd800000,0xbd35bd35,0x3cc4bd6d,0x3d6dbcc4,0x3d6d3cc4,0x3cc43d6d,0x8000bd80,0x3d35bd35,0x3d800000,0x3d353d35,
0x3d800000,0xbcc43d6d,0xbd35bd35,0x3d6dbcc4,0x3d0e3d55,0xbd7b3c48,0x3c48bd7b,0x3d553d0e,0x8000bd80,0x3d6d3cc4,0xbd353d35,0xbcc4bd6d,0x3d55bd0e,0x3c483d7b,0xbd7bbc48,0x3d0ebd55,
0xbd800000,0x3cc4bd6d,0x3d353d35,0xbd6d3cc4,0xbd0ebd55,0x3d7bbc48,0xbc483d7b,0xbd55bd0e,0x80003d80,0xbd6dbcc4,0x3d35bd35,0x3cc43d6d,0xbd553d0e,0xbc48bd7b,0x3d7b3c48,0xbd0e3d55,
0x3d7b3c48,0x3d553d0e,0x3d0e3d55,0x3c483d7b,0x3d800000,0x3d6d3cc4,0x3d353d35,0x3cc43d6d,0x3c48bd7b,0x3d0ebd55,0x3d55bd0e,0x3d7bbc48,0x8000bd80,0x3cc4bd6d,0x3d35bd35,0x3d6dbcc4,
0xbd7bbc48,0xbd55bd0e,0xbd0ebd55,0xbc48bd7b,0xbd800000,0xbd6dbcc4,0xbd35bd35,0xbcc4bd6d,0xbc483d7b,0xbd0e3d55,0xbd553d0e,0xbd7b3c48,0x80003d80,0xbcc43d6d,0xbd353d35,0xbd6d3cc4,
0x3d800000,0xbd800000,0x3d800000,0xbd800000,0x3d80,0xbd80,0x3d80,0xbd80,0x3d800000,0xbd800000,0x3d800000,0xbd800000,0x3d80,0xbd80,0x3d80,0xbd80,
0x3d800000,0xbd800000,0x3d800000,0xbd800000,0x3d80,0xbd80,0x3d80,0xbd80,0x3d800000,0xbd800000,0x3d800000,0xbd800000,0x3d80,0xbd80,0x3d80,0xbd80,
0x3d353d35,0xbd353d35,0xbd35bd35,0x3d35bd35,0x3d800000,0x3d80,0xbd800000,0xbd80,0x3d353d35,0xbd353d35,0xbd35bd35,0x3d35bd35,0x3d800000,0x3d80,0xbd800000,0xbd80,
0x3d353d35,0xbd353d35,0xbd35bd35,0x3d35bd35,0x3d800000,0x3d80,0xbd800000,0xbd80,0x3d353d35,0xbd353d35,0xbd35bd35,0x3d35bd35,0x3d800000,0x3d80,0xbd800000,0xbd80,
0xbd80,0x3cc43d6d,0xbd35bd35,0x3d6d3cc4,0x3d7bbc48,0xbd553d0e,0x3d0ebd55,0xbc483d7b,0x3d800000,0xbd6d3cc4,0x3d35bd35,0xbcc43d6d,0x3c483d7b,0xbd0ebd55,0x3d553d0e,0xbd7bbc48,
0x3d80,0xbcc4bd6d,0x3d353d35,0xbd6dbcc4,0xbd7b3c48,0x3d55bd0e,0xbd0e3d55,0x3c48bd7b,0xbd800000,0x3d6dbcc4,0xbd353d35,0x3cc4bd6d,0xbc48bd7b,0x3d0e3d55,0xbd55bd0e,0x3d7b3c48,
0x3d0ebd55,0x3d7b3c48,0x3c483d7b,0xbd553d0e,0xbd80,0x3d6dbcc4,0x3d353d35,0xbcc43d6d,0x3d553d0e,0xbc483d7b,0xbd7b3c48,0xbd0ebd55,0x3d800000,0x3cc43d6d,0xbd353d35,0xbd6dbcc4,
0xbd0e3d55,0xbd7bbc48,0xbc48bd7b,0x3d55bd0e,0x3d80,0xbd6d3cc4,0xbd35bd35,0x3cc4bd6d,0xbd55bd0e,0x3c48bd7b,0x3d7bbc48,0x3d0e3d55,0xbd800000,0xbcc4bd6d,0x3d35bd35,0x3d6d3cc4,
0x3d800000,0xbd353d35,0xbd80,0x3d353d35,0x3cc43d6d,0xbd6dbcc4,0x3d6dbcc4,0xbcc43d6d,0xbd800000,0x3d35bd35,0x3d80,0xbd35bd35,0xbcc4bd6d,0x3d6d3cc4,0xbd6d3cc4,0x3cc4bd6d,
0x3d800000,0xbd353d35,0xbd80,0x3d353d35,0x3cc43d6d,0xbd6dbcc4,0x3d6dbcc4,0xbcc43d6d,0xbd800000,0x3d35bd35,0x3d80,0xbd35bd35,0xbcc4bd6d,0x3d6d3cc4,0xbd6d3cc4,0x3cc4bd6d,
0x3d6d3cc4,0x3cc43d6d,0xbcc43d6d,0xbd6d3cc4,0x3d800000,0x3d353d35,0x3d80,0xbd353d35,0xbd6dbcc4,0xbcc4bd6d,0x3cc4bd6d,0x3d6dbcc4,0xbd800000,0xbd35bd35,0xbd80,0x3d35bd35,
0x3d6d3cc4,0x3cc43d6d,0xbcc43d6d,0xbd6d3cc4,0x3d800000,0x3d353d35,0x3d80,0xbd353d35,0xbd6dbcc4,0xbcc4bd6d,0x3cc4bd6d,0x3d6dbcc4,0xbd800000,0xbd35bd35,0xbd80,0x3d35bd35,
0xbd80,0x3d6d3cc4,0xbd353d35,0xbcc4bd6d,0x3d55bd0e,0x3c483d7b,0xbd7bbc48,0x3d0ebd55,0xbd800000,0x3cc4bd6d,0x3d353d35,0xbd6d3cc4,0xbd0ebd55,0x3d7bbc48,0xbc483d7b,0xbd55bd0e,
0x3d80,0xbd6dbcc4,0x3d35bd35,0x3cc43d6d,0xbd553d0e,0xbc48bd7b,0x3d7b3c48,0xbd0e3d55,0x3d800000,0xbcc43d6d,0xbd35bd35,0x3d6dbcc4,0x3d0e3d55,0xbd7b3c48,0x3c48bd7b,0x3d553d0e,
0x3c48bd7b,0x3d0ebd55,0x3d55bd0e,0x3d7bbc48,0xbd80,0x3cc4bd6d,0x3d35bd35,0x3d6dbcc4,0xbd7bbc48,0xbd55bd0e,0xbd0ebd55,0xbc48bd7b,0xbd800000,0xbd6dbcc4,0xbd35bd35,0xbcc4bd6d,
0xbc483d7b,0xbd0e3d55,0xbd553d0e,0xbd7b3c48,0x3d80,0xbcc43d6d,0xbd353d35,0xbd6d3cc4,0x3d7b3c48,0x3d553d0e,0x3d0e3d55,0x3c483d7b,0x3d800000,0x3d6d3cc4,0x3d353d35,0x3cc43d6d,
0x3d80,0x3d80,0x3d80,0x3d80,0x3d80,0x3d80,0x3d80,0x3d80,0x3d80,0x3d80,0x3d80,0x3d80,0x3d80,0x3d80,0x3d80,0x3d80,
0x3d80,0x3d80,0x3d80,0x3d80,0x3d80,0x3d80,0x3d80,0x3d80,0x3d80,0x3d80,0x3d80,0x3d80,0x3d80,0x3d80,0x3d80,0x3d80,
0xbd353d35,0xbd553d0e,0xbd6d3cc4,0xbd7b3c48,0x3d80,0xbc483d7b,0xbcc43d6d,0xbd0e3d55,0xbd35bd35,0xbd0ebd55,0xbcc4bd6d,0xbc48bd7b,0xbd800000,0xbd7bbc48,0xbd6dbcc4,0xbd55bd0e,
0x3d35bd35,0x3d55bd0e,0x3d6dbcc4,0x3d7bbc48,0xbd80,0x3c48bd7b,0x3cc4bd6d,0x3d0ebd55,0x3d353d35,0x3d0e3d55,0x3cc43d6d,0x3c483d7b,0x3d800000,0x3d7b3c48,0x3d6d3cc4,0x3d553d0e,
0xbd80,0x3cc4bd6d,0x3d35bd35,0x3d6dbcc4,0x3d800000,0x3d6d3cc4,0x3d353d35,0x3cc43d6d,0x3d80,0xbcc43d6d,0xbd353d35,0xbd6d3cc4,0xbd800000,0xbd6dbcc4,0xbd35bd35,0xbcc4bd6d,
0xbd80,0x3cc4bd6d,0x3d35bd35,0x3d6dbcc4,0x3d800000,0x3d6d3cc4,0x3d353d35,0x3cc43d6d,0x3d80,0xbcc43d6d,0xbd353d35,0xbd6d3cc4,0xbd800000,0xbd6dbcc4,0xbd35bd35,0xbcc4bd6d,
0xbd353d35,0xbd7b3c48,0xbd6dbcc4,0xbd0ebd55,0x3d800000,0x3d553d0e,0x3cc43d6d,0xbc483d7b,0xbd35bd35,0xbc48bd7b,0x3cc4bd6d,0x3d55bd0e,0x3d80,0xbd0e3d55,0xbd6d3cc4,0xbd7bbc48,
0x3d35bd35,0x3d7bbc48,0x3d6d3cc4,0x3d0e3d55,0xbd800000,0xbd55bd0e,0xbcc4bd6d,0x3c48bd7b,0x3d353d35,0x3c483d7b,0xbcc43d6d,0xbd553d0e,0xbd80,0x3d0ebd55,0x3d6dbcc4,0x3d7b3c48,
0x3d80,0xbd353d35,0xbd800000,0xbd35bd35,0xbd80,0x3d35bd35,0x3d800000,0x3d353d35,0x3d80,0xbd353d35,0xbd800000,0xbd35bd35,0xbd80,0x3d35bd35,0x3d800000,0x3d353d35,
0x3d80,0xbd353d35,0xbd800000,0xbd35bd35,0xbd80,0x3d35bd35,0x3d800000,0x3d353d35,0x3d80,0xbd353d35,0xbd800000,0xbd35bd35,0xbd80,0x3d35bd35,0x3d800000,0x3d353d35,
0xbd353d35,0xbd7bbc48,0xbcc4bd6d,0x3d0ebd55,0xbd80,0x3d55bd0e,0x3d6d3cc4,0x3c483d7b,0xbd35bd35,0x3c48bd7b,0x3d6dbcc4,0x3d553d0e,0x3d800000,0x3d0e3d55,0xbcc43d6d,0xbd7b3c48,
0x3d35bd35,0x3d7b3c48,0x3cc43d6d,0xbd0e3d55,0x3d80,0xbd553d0e,0xbd6dbcc4,0xbc48bd7b,0x3d353d35,0xbc483d7b,0xbd6d3cc4,0xbd55bd0e,0xbd800000,0xbd0ebd55,0x3cc4bd6d,0x3d7bbc48,
0xbd80,0x3d6dbcc4,0x3d353d35,0xbcc43d6d,0xbd800000,0xbcc4bd6d,0x3d35bd35,0x3d6d3cc4,0x3d80,0xbd6d3cc4,0xbd35bd35,0x3cc4bd6d,0x3d800000,0x3cc43d6d,0xbd353d35,0xbd6dbcc4,
0xbd80,0x3d6dbcc4,0x3d353d35,0xbcc43d6d,0xbd800000,0xbcc4bd6d,0x3d35bd35,0x3d6d3cc4,0x3d80,0xbd6d3cc4,0xbd35bd35,0x3cc4bd6d,0x3d800000,0x3cc43d6d,0xbd353d35,0xbd6dbcc4,
0xbd353d35,0xbd55bd0e,0x3cc4bd6d,0x3d7b3c48,0xbd800000,0xbc48bd7b,0x3d6dbcc4,0x3d0e3d55,0xbd35bd35,0x3d0ebd55,0x3d6d3cc4,0xbc483d7b,0xbd80,0x3d7bbc48,0x3cc43d6d,0xbd553d0e,
0x3d35bd35,0x3d553d0e,0xbcc43d6d,0xbd7bbc48,0x3d800000,0x3c483d7b,0xbd6d3cc4,0xbd0ebd55,0x3d353d35,0xbd0e3d55,0xbd6dbcc4,0x3c48bd7b,0x3d80,0xbd7b3c48,0xbcc4bd6d,0x3d55bd0e,
0xbd800000,0xbd800000,0xbd800000,0xbd800000,0xbd800000,0xbd800000,0xbd800000,0xbd800000,0xbd800000,0xbd800000,0xbd800000,0xbd800000,0xbd800000,0xbd800000,0xbd800000,0xbd800000,
0xbd800000,0xbd800000,0xbd800000,0xbd800000,0xbd800000,0xbd800000,0xbd800000,0xbd800000,0xbd800000,0xbd800000,0xbd800000,0xbd800000,0xbd800000,0xbd800000,0xbd800000,0xbd800000,
0xbd35bd35,0xbd0ebd55,0xbcc4bd6d,0xbc48bd7b,0xbd800000,0xbd7bbc48,0xbd6dbcc4,0xbd55bd0e,0x3d35bd35,0x3d55bd0e,0x3d6dbcc4,0x3d7bbc48,0x8000bd80,0x3c48bd7b,0x3cc4bd6d,0x3d0ebd55,
0x3d353d35,0x3d0e3d55,0x3cc43d6d,0x3c483d7b,0x3d800000,0x3d7b3c48,0x3d6d3cc4,0x3d553d0e,0xbd353d35,0xbd553d0e,0xbd6d3cc4,0xbd7b3c48,0x80003d80,0xbc483d7b,0xbcc43d6d,0xbd0e3d55,
0x3d800000,0x3d6d3cc4,0x3d353d35,0x3cc43d6d,0x80003d80,0xbcc43d6d,0xbd353d35,0xbd6d3cc4,0xbd800000,0xbd6dbcc4,0xbd35bd35,0xbcc4bd6d,0x8000bd80,0x3cc4bd6d,0x3d35bd35,0x3d6dbcc4,
0x3d800000,0x3d6d3cc4,0x3d353d35,0x3cc43d6d,0x80003d80,0xbcc43d6d,0xbd353d35,0xbd6d3cc4,0xbd800000,0xbd6dbcc4,0xbd35bd35,0xbcc4bd6d,0x8000bd80,0x3cc4bd6d,0x3d35bd35,0x3d6dbcc4,
0xbd35bd35,0xbc48bd7b,0x3cc4bd6d,0x3d55bd0e,0x80003d80,0xbd0e3d55,0xbd6d3cc4,0xbd7bbc48,0x3d35bd35,0x3d7bbc48,0x3d6d3cc4,0x3d0e3d55,0xbd800000,0xbd55bd0e,0xbcc4bd6d,0x3c48bd7b,
0x3d353d35,0x3c483d7b,0xbcc43d6d,0xbd553d0e,0x8000bd80,0x3d0ebd55,0x3d6dbcc4,0x3d7b3c48,0xbd353d35,0xbd7b3c48,0xbd6dbcc4,0xbd0ebd55,0x3d800000,0x3d553d0e,0x3cc43d6d,0xbc483d7b,
0xbd800000,0xbd35bd35,0x8000bd80,0x3d35bd35,0x3d800000,0x3d353d35,0x80003d80,0xbd353d35,0xbd800000,0xbd35bd35,0x8000bd80,0x3d35bd35,0x3d800000,0x3d353d35,0x80003d80,0xbd353d35,
0xbd800000,0xbd35bd35,0x8000bd80,0x3d35bd35,0x3d800000,0x3d353d35,0x80003d80,0xbd353d35,0xbd800000,0xbd35bd35,0x8000bd80,0x3d35bd35,0x3d800000,0x3d353d35,0x80003d80,0xbd353d35,
0xbd35bd35,0x3c48bd7b,0x3d6dbcc4,0x3d553d0e,0x3d800000,0x3d0e3d55,0xbcc43d6d,0xbd7b3c48,0x3d35bd35,0x3d7b3c48,0x3cc43d6d,0xbd0e3d55,0x80003d80,0xbd553d0e,0xbd6dbcc4,0xbc48bd7b,
0x3d353d35,0xbc483d7b,0xbd6d3cc4,0xbd55bd0e,0xbd800000,0xbd0ebd55,0x3cc4bd6d,0x3d7bbc48,0xbd353d35,0xbd7bbc48,0xbcc4bd6d,0x3d0ebd55,0x8000bd80,0x3d55bd0e,0x3d6d3cc4,0x3c483d7b,
0x3d800000,0x3cc43d6d,0xbd353d35,0xbd6dbcc4,0x8000bd80,0x3d6dbcc4,0x3d353d35,0xbcc43d6d,0xbd800000,0xbcc4bd6d,0x3d35bd35,0x3d6d3cc4,0x80003d80,0xbd6d3cc4,0xbd35bd35,0x3cc4bd6d,
0x3d800000,0x3cc43d6d,0xbd353d35,0xbd6dbcc4,0x8000bd80,0x3d6dbcc4,0x3d353d35,0xbcc43d6d,0xbd800000,0xbcc4bd6d,0x3d35bd35,0x3d6d3cc4,0x80003d80,0xbd6d3cc4,0xbd35bd35,0x3cc4bd6d,
0xbd35bd35,0x3d0ebd55,0x3d6d3cc4,0xbc483d7b,0x8000bd80,0x3d7bbc48,0x3cc43d6d,0xbd553d0e,0x3d35bd35,0x3d553d0e,0xbcc43d6d,0xbd7bbc48,0x3d800000,0x3c483d7b,0xbd6d3cc4,0xbd0ebd55,
0x3d353d35,0xbd0e3d55,0xbd6dbcc4,0x3c48bd7b,0x80003d80,0xbd7b3c48,0xbcc4bd6d,0x3d55bd0e,0xbd353d35,0xbd55bd0e,0x3cc4bd6d,0x3d7b3c48,0xbd800000,0xbc48bd7b,0x3d6dbcc4,0x3d0e3d55,
0x3d80,0xbd800000,0xbd80,0x3d800000,0x3d80,0xbd800000,0xbd80,0x3d800000,0x3d80,0xbd800000,0xbd80,0x3d800000,0x3d80,0xbd800000,0xbd80,0x3d800000,
0x3d80,0xbd800000,0xbd80,0x3d800000,0x3d80,0xbd800000,0xbd80,0x3d800000,0x3d80,0xbd800000,0xbd80,0x3d800000,0x3d80,0xbd800000,0xbd80,0x3d800000,
0xbd353d35,0xbd0ebd55,0x3d6dbcc4,0x3c483d7b,0x3d80,0xbd7bbc48,0x3cc4bd6d,0x3d553d0e,0xbd35bd35,0x3d55bd0e,0x3cc43d6d,0xbd7b3c48,0xbd800000,0x3c48bd7b,0x3d6d3cc4,0xbd0e3d55,
0x3d35bd35,0x3d0e3d55,0xbd6d3cc4,0xbc48bd7b,0xbd80,0x3d7b3c48,0xbcc43d6d,0xbd55bd0e,0x3d353d35,0xbd553d0e,0xbcc4bd6d,0x3d7bbc48,0x3d800000,0xbc483d7b,0xbd6dbcc4,0x3d0ebd55,
0xbd80,0x3d6d3cc4,0xbd353d35,0xbcc4bd6d,0x3d800000,0xbcc43d6d,0xbd35bd35,0x3d6dbcc4,0x3d80,0xbd6dbcc4,0x3d35bd35,0x3cc43d6d,0xbd800000,0x3cc4bd6d,0x3d353d35,0xbd6d3cc4,
0xbd80,0x3d6d3cc4,0xbd353d35,0xbcc4bd6d,0x3d800000,0xbcc43d6d,0xbd35bd35,0x3d6dbcc4,0x3d80,0xbd6dbcc4,0x3d35bd35,0x3cc43d6d,0xbd800000,0x3cc4bd6d,0x3d353d35,0xbd6d3cc4,
0xbd353d35,0xbc48bd7b,0x3d6d3cc4,0xbd553d0e,0x3d800000,0xbd0e3d55,0xbcc4bd6d,0x3d7b3c48,0xbd35bd35,0x3d7bbc48,0xbcc43d6d,0xbd0ebd55,0x3d80,0xbd55bd0e,0x3d6dbcc4,0xbc483d7b,
0x3d35bd35,0x3c483d7b,0xbd6dbcc4,0x3d55bd0e,0xbd800000,0x3d0ebd55,0x3cc43d6d,0xbd7bbc48,0x3d353d35,0xbd7b3c48,0x3cc4bd6d,0x3d0e3d55,0xbd80,0x3d553d0e,0xbd6d3cc4,0x3c48bd7b,
0x3d80,0xbd35bd35,0x3d800000,0xbd353d35,0xbd80,0x3d353d35,0xbd800000,0x3d35bd35,0x3d80,0xbd35bd35,0x3d800000,0xbd353d35,0xbd80,0x3d353d35,0xbd800000,0x3d35bd35,
0x3d80,0xbd35bd35,0x3d800000,0xbd353d35,0xbd80,0x3d353d35,0xbd800000,0x3d35bd35,0x3d80,0xbd35bd35,0x3d800000,0xbd353d35,0xbd80,0x3d353d35,0xbd800000,0x3d35bd35,
0xbd353d35,0x3c48bd7b,0x3cc43d6d,0xbd55bd0e,0xbd80,0x3d0e3d55,0xbd6dbcc4,0x3d7bbc48,0xbd35bd35,0x3d7b3c48,0xbd6d3cc4,0x3d0ebd55,0x3d800000,0xbd553d0e,0x3cc4bd6d,0x3c483d7b,
0x3d35bd35,0xbc483d7b,0xbcc4bd6d,0x3d553d0e,0x3d80,0xbd0ebd55,0x3d6d3cc4,0xbd7b3c48,0x3d353d35,0xbd7bbc48,0x3d6dbcc4,0xbd0e3d55,0xbd800000,0x3d55bd0e,0xbcc43d6d,0xbc48bd7b,
0xbd80,0x3cc43d6d,0xbd35bd35,0x3d6d3cc4,0xbd800000,0x3d6dbcc4,0xbd353d35,0x3cc4bd6d,0x3d80,0xbcc4bd6d,0x3d353d35,0xbd6dbcc4,0x3d800000,0xbd6d3cc4,0x3d35bd35,0xbcc43d6d,
0xbd80,0x3cc43d6d,0xbd35bd35,0x3d6d3cc4,0xbd800000,0x3d6dbcc4,0xbd353d35,0x3cc4bd6d,0x3d80,0xbcc4bd6d,0x3d353d35,0xbd6dbcc4,0x3d800000,0xbd6d3cc4,0x3d35bd35,0xbcc43d6d,
0xbd353d35,0x3d0ebd55,0xbcc43d6d,0x3c48bd7b,0xbd800000,0x3d7bbc48,0xbd6d3cc4,0x3d55bd0e,0xbd35bd35,0x3d553d0e,0xbd6dbcc4,0x3d7b3c48,0xbd80,0x3c483d7b,0xbcc4bd6d,0x3d0e3d55,
0x3d35bd35,0xbd0e3d55,0x3cc4bd6d,0xbc483d7b,0x3d800000,0xbd7b3c48,0x3d6dbcc4,0xbd553d0e,0x3d353d35,0xbd55bd0e,0x3d6d3cc4,0xbd7bbc48,0x3d80,0xbc48bd7b,0x3cc43d6d,0xbd0ebd55,
0xbd800000,0x8000bd80,0x3d800000,0x80003d80,0xbd800000,0x8000bd80,0x3d800000,0x80003d80,0xbd800000,0x8000bd80,0x3d800000,0x80003d80,0xbd800000,0x8000bd80,0x3d800000,0x80003d80,
0xbd800000,0x8000bd80,0x3d800000,0x80003d80,0xbd800000,0x8000bd80,0x3d800000,0x80003d80,0xbd800000,0x8000bd80,0x3d800000,0x80003d80,0xbd800000,0x8000bd80,0x3d800000,0x80003d80,
0xbd35bd35,0x3d55bd0e,0x3cc43d6d,0xbd7b3c48,0xbd800000,0x3c48bd7b,0x3d6d3cc4,0xbd0e3d55,0x3d35bd35,0x3d0e3d55,0xbd6d3cc4,0xbc48bd7b,0x8000bd80,0x3d7b3c48,0xbcc43d6d,0xbd55bd0e,
0x3d353d35,0xbd553d0e,0xbcc4bd6d,0x3d7bbc48,0x3d800000,0xbc483d7b,0xbd6dbcc4,0x3d0ebd55,0xbd353d35,0xbd0ebd55,0x3d6dbcc4,0x3c483d7b,0x80003d80,0xbd7bbc48,0x3cc4bd6d,0x3d553d0e,
0x3d800000,0xbcc43d6d,0xbd35bd35,0x3d6dbcc4,0x80003d80,0xbd6dbcc4,0x3d35bd35,0x3cc43d6d,0xbd800000,0x3cc4bd6d,0x3d353d35,0xbd6d3cc4,0x8000bd80,0x3d6d3cc4,0xbd353d35,0xbcc4bd6d,
0x3d800000,0xbcc43d6d,0xbd35bd35,0x3d6dbcc4,0x80003d80,0xbd6dbcc4,0x3d35bd35,0x3cc43d6d,0xbd800000,0x3cc4bd6d,0x3d353d35,0xbd6d3cc4,0x8000bd80,0x3d6d3cc4,0xbd353d35,0xbcc4bd6d,
0xbd35bd35,0x3d7bbc48,0xbcc43d6d,0xbd0ebd55,0x80003d80,0xbd55bd0e,0x3d6dbcc4,0xbc483d7b,0x3d35bd35,0x3c483d7b,0xbd6dbcc4,0x3d55bd0e,0xbd800000,0x3d0ebd55,0x3cc43d6d,0xbd7bbc48,
0x3d353d35,0xbd7b3c48,0x3cc4bd6d,0x3d0e3d55,0x8000bd80,0x3d553d0e,0xbd6d3cc4,0x3c48bd7b,0xbd353d35,0xbc48bd7b,0x3d6d3cc4,0xbd553d0e,0x3d800000,0xbd0e3d55,0xbcc4bd6d,0x3d7b3c48,
0xbd800000,0x3d35bd35,0x80003d80,0xbd35bd35,0x3d800000,0xbd353d35,0x8000bd80,0x3d353d35,0xbd800000,0x3d35bd35,0x80003d80,0xbd35bd35,0x3d800000,0xbd353d35,0x8000bd80,0x3d353d35,
0xbd800000,0x3d35bd35,0x80003d80,0xbd35bd35,0x3d800000,0xbd353d35,0x8000bd80,0x3d353d35,0xbd800000,0x3d35bd35,0x80003d80,0xbd35bd35,0x3d800000,0xbd353d35,0x8000bd80,0x3d353d35,
0xbd35bd35,0x3d7b3c48,0xbd6d3cc4,0x3d0ebd55,0x3d800000,0xbd553d0e,0x3cc4bd6d,0x3c483d7b,0x3d35bd35,0xbc483d7b,0xbcc4bd6d,0x3d553d0e,0x80003d80,0xbd0ebd55,0x3d6d3cc4,0xbd7b3c48,
0x3d353d35,0xbd7bbc48,0x3d6dbcc4,0xbd0e3d55,0xbd800000,0x3d55bd0e,0xbcc43d6d,0xbc48bd7b,0xbd353d35,0x3c48bd7b,0x3cc43d6d,0xbd55bd0e,0x8000bd80,0x3d0e3d55,0xbd6dbcc4,0x3d7bbc48,
0x3d800000,0xbd6d3cc4,0x3d35bd35,0xbcc43d6d,0x8000bd80,0x3cc43d6d,0xbd35bd35,0x3d6d3cc4,0xbd800000,0x3d6dbcc4,0xbd353d35,0x3cc4bd6d,0x80003d80,0xbcc4bd6d,0x3d353d35,0xbd6dbcc4,
0x3d800000,0xbd6d3cc4,0x3d35bd35,0xbcc43d6d,0x8000bd80,0x3cc43d6d,0xbd35bd35,0x3d6d3cc4,0xbd800000,0x3d6dbcc4,0xbd353d35,0x3cc4bd6d,0x80003d80,0xbcc4bd6d,0x3d353d35,0xbd6dbcc4,
0xbd35bd35,0x3d553d0e,0xbd6dbcc4,0x3d7b3c48,0x8000bd80,0x3c483d7b,0xbcc4bd6d,0x3d0e3d55,0x3d35bd35,0xbd0e3d55,0x3cc4bd6d,0xbc483d7b,0x3d800000,0xbd7b3c48,0x3d6dbcc4,0xbd553d0e,
0x3d353d35,0xbd55bd0e,0x3d6d3cc4,0xbd7bbc48,0x80003d80,0xbc48bd7b,0x3cc43d6d,0xbd0ebd55,0xbd353d35,0x3d0ebd55,0xbcc43d6d,0x3c48bd7b,0xbd800000,0x3d7bbc48,0xbd6d3cc4,0x3d55bd0e,
0x3d80,0xbd80,0x3d80,0xbd80,0x3d80,0xbd80,0x3d80,0xbd80,0x3d80,0xbd80,0x3d80,0xbd80,0x3d80,0xbd80,0x3d80,0xbd80,
0x3d80,0xbd80,0x3d80,0xbd80,0x3d80,0xbd80,0x3d80,0xbd80,0x3d80,0xbd80,0x3d80,0xbd80,0x3d80,0xbd80,0x3d80,0xbd80,
0xbd353d35,0x3d55bd0e,0xbd6d3cc4,0x3d7bbc48,0x3d80,0x3c48bd7b,0xbcc43d6d,0x3d0ebd55,0xbd35bd35,0x3d0e3d55,0xbcc4bd6d,0x3c483d7b,0xbd800000,0x3d7b3c48,0xbd6dbcc4,0x3d553d0e,
0x3d35bd35,0xbd553d0e,0x3d6dbcc4,0xbd7b3c48,0xbd80,0xbc483d7b,0x3cc4bd6d,0xbd0e3d55,0x3d353d35,0xbd0ebd55,0x3cc43d6d,0xbc48bd7b,0x3d800000,0xbd7bbc48,0x3d6d3cc4,0xbd55bd0e,
0xbd80,0xbcc43d6d,0x3d35bd35,0xbd6d3cc4,0x3d800000,0xbd6dbcc4,0x3d353d35,0xbcc4bd6d,0x3d80,0x3cc4bd6d,0xbd353d35,0x3d6dbcc4,0xbd800000,0x3d6d3cc4,0xbd35bd35,0x3cc43d6d,
0xbd80,0xbcc43d6d,0x3d35bd35,0xbd6d3cc4,0x3d800000,0xbd6dbcc4,0x3d353d35,0xbcc4bd6d,0x3d80,0x3cc4bd6d,0xbd353d35,0x3d6dbcc4,0xbd800000,0x3d6d3cc4,0xbd35bd35,0x3cc43d6d,
0xbd353d35,0x3d7bbc48,0xbd6dbcc4,0x3d0e3d55,0x3d800000,0xbd55bd0e,0x3cc43d6d,0x3c48bd7b,0xbd35bd35,0x3c483d7b,0x3cc4bd6d,0xbd553d0e,0x3d80,0x3d0ebd55,0xbd6d3cc4,0x3d7b3c48,
0x3d35bd35,0xbd7b3c48,0x3d6d3cc4,0xbd0ebd55,0xbd800000,0x3d553d0e,0xbcc4bd6d,0xbc483d7b,0x3d353d35,0xbc48bd7b,0xbcc43d6d,0x3d55bd0e,0xbd80,0xbd0e3d55,0x3d6dbcc4,0xbd7bbc48,
0x3d80,0x3d35bd35,0xbd800000,0x3d353d35,0xbd80,0xbd353d35,0x3d800000,0xbd35bd35,0x3d80,0x3d35bd35,0xbd800000,0x3d353d35,0xbd80,0xbd353d35,0x3d800000,0xbd35bd35,
0x3d80,0x3d35bd35,0xbd800000,0x3d353d35,0xbd80,0xbd353d35,0x3d800000,0xbd35bd35,0x3d80,0x3d35bd35,0xbd800000,0x3d353d35,0xbd80,0xbd353d35,0x3d800000,0xbd35bd35,
0xbd353d35,0x3d7b3c48,0xbcc4bd6d,0xbd0e3d55,0xbd80,0xbd553d0e,0x3d6d3cc4,0xbc48bd7b,0xbd35bd35,0xbc483d7b,0x3d6dbcc4,0xbd55bd0e,0x3d800000,0xbd0ebd55,0xbcc43d6d,0x3d7bbc48,
0x3d35bd35,0xbd7bbc48,0x3cc43d6d,0x3d0ebd55,0x3d80,0x3d55bd0e,0xbd6dbcc4,0x3c483d7b,0x3d353d35,0x3c48bd7b,0xbd6d3cc4,0x3d553d0e,0xbd800000,0x3d0e3d55,0x3cc4bd6d,0xbd7b3c48,
0xbd80,0xbd6d3cc4,0x3d353d35,0x3cc4bd6d,0xbd800000,0x3cc43d6d,0x3d35bd35,0xbd6dbcc4,0x3d80,0x3d6dbcc4,0xbd35bd35,0xbcc43d6d,0x3d800000,0xbcc4bd6d,0xbd353d35,0x3d6d3cc4,
0xbd80,0xbd6d3cc4,0x3d353d35,0x3cc4bd6d,0xbd800000,0x3cc43d6d,0x3d35bd35,0xbd6dbcc4,0x3d80,0x3d6dbcc4,0xbd35bd35,0xbcc43d6d,0x3d800000,0xbcc4bd6d,0xbd353d35,0x3d6d3cc4,
0xbd353d35,0x3d553d0e,0x3cc4bd6d,0xbd7bbc48,0xbd800000,0x3c483d7b,0x3d6dbcc4,0xbd0ebd55,0xbd35bd35,0xbd0e3d55,0x3d6d3cc4,0x3c48bd7b,0xbd80,0xbd7b3c48,0x3cc43d6d,0x3d55bd0e,
0x3d35bd35,0xbd55bd0e,0xbcc43d6d,0x3d7b3c48,0x3d800000,0xbc48bd7b,0xbd6d3cc4,0x3d0e3d55,0x3d353d35,0x3d0ebd55,0xbd6dbcc4,0xbc483d7b,0x3d80,0x3d7bbc48,0xbcc4bd6d,0xbd553d0e,
0xbd800000,0x3d800000,0xbd800000,0x3d800000,0xbd800000,0x3d800000,0xbd800000,0x3d800000,0xbd800000,0x3d800000,0xbd800000,0x3d800000,0xbd800000,0x3d800000,0xbd800000,0x3d800000,
0xbd800000,0x3d800000,0xbd800000,0x3d800000,0xbd800000,0x3d800000,0xbd800000,0x3d800000,0xbd800000,0x3d800000,0xbd800000,0x3d800000,0xbd800000,0x3d800000,0xbd800000,0x3d800000,
0xbd35bd35,0x3d0e3d55,0xbcc4bd6d,0x3c483d7b,0xbd800000,0x3d7b3c48,0xbd6dbcc4,0x3d553d0e,0x3d35bd35,0xbd553d0e,0x3d6dbcc4,0xbd7b3c48,0x8000bd80,0xbc483d7b,0x3cc4bd6d,0xbd0e3d55,
0x3d353d35,0xbd0ebd55,0x3cc43d6d,0xbc48bd7b,0x3d800000,0xbd7bbc48,0x3d6d3cc4,0xbd55bd0e,0xbd353d35,0x3d55bd0e,0xbd6d3cc4,0x3d7bbc48,0x80003d80,0x3c48bd7b,0xbcc43d6d,0x3d0ebd55,
0x3d800000,0xbd6dbcc4,0x3d353d35,0xbcc4bd6d,0x80003d80,0x3cc4bd6d,0xbd353d35,0x3d6dbcc4,0xbd800000,0x3d6d3cc4,0xbd35bd35,0x3cc43d6d,0x8000bd80,0xbcc43d6d,0x3d35bd35,0xbd6d3cc4,
0x3d800000,0xbd6dbcc4,0x3d353d35,0xbcc4bd6d,0x80003d80,0x3cc4bd6d,0xbd353d35,0x3d6dbcc4,0xbd800000,0x3d6d3cc4,0xbd35bd35,0x3cc43d6d,0x8000bd80,0xbcc43d6d,0x3d35bd35,0xbd6d3cc4,
0xbd35bd35,0x3c483d7b,0x3cc4bd6d,0xbd553d0e,0x80003d80,0x3d0ebd55,0xbd6d3cc4,0x3d7b3c48,0x3d35bd35,0xbd7b3c48,0x3d6d3cc4,0xbd0ebd55,0xbd800000,0x3d553d0e,0xbcc4bd6d,0xbc483d7b,
0x3d353d35,0xbc48bd7b,0xbcc43d6d,0x3d55bd0e,0x8000bd80,0xbd0e3d55,0x3d6dbcc4,0xbd7bbc48,0xbd353d35,0x3d7bbc48,0xbd6dbcc4,0x3d0e3d55,0x3d800000,0xbd55bd0e,0x3cc43d6d,0x3c48bd7b,
0xbd800000,0x3d353d35,0x8000bd80,0xbd353d35,0x3d800000,0xbd35bd35,0x80003d80,0x3d35bd35,0xbd800000,0x3d353d35,0x8000bd80,0xbd353d35,0x3d800000,0xbd35bd35,0x80003d80,0x3d35bd35,
0xbd800000,0x3d353d35,0x8000bd80,0xbd353d35,0x3d800000,0xbd35bd35,0x80003d80,0x3d35bd35,0xbd800000,0x3d353d35,0x8000bd80,0xbd353d35,0x3d800000,0xbd35bd35,0x80003d80,0x3d35bd35,
0xbd35bd35,0xbc483d7b,0x3d6dbcc4,0xbd55bd0e,0x3d800000,0xbd0ebd55,0xbcc43d6d,0x3d7bbc48,0x3d35bd35,0xbd7bbc48,0x3cc43d6d,0x3d0ebd55,0x80003d80,0x3d55bd0e,0xbd6dbcc4,0x3c483d7b,
0x3d353d35,0x3c48bd7b,0xbd6d3cc4,0x3d553d0e,0xbd800000,0x3d0e3d55,0x3cc4bd6d,0xbd7b3c48,0xbd353d35,0x3d7b3c48,0xbcc4bd6d,0xbd0e3d55,0x8000bd80,0xbd553d0e,0x3d6d3cc4,0xbc48bd7b,
0x3d800000,0xbcc4bd6d,0xbd353d35,0x3d6d3cc4,0x8000bd80,0xbd6d3cc4,0x3d353d35,0x3cc4bd6d,0xbd800000,0x3cc43d6d,0x3d35bd35,0xbd6dbcc4,0x80003d80,0x3d6dbcc4,0xbd35bd35,0xbcc43d6d,
0x3d800000,0xbcc4bd6d,0xbd353d35,0x3d6d3cc4,0x8000bd80,0xbd6d3cc4,0x3d353d35,0x3cc4bd6d,0xbd800000,0x3cc43d6d,0x3d35bd35,0xbd6dbcc4,0x80003d80,0x3d6dbcc4,0xbd35bd35,0xbcc43d6d,
0xbd35bd35,0xbd0e3d55,0x3d6d3cc4,0x3c48bd7b,0x8000bd80,0xbd7b3c48,0x3cc43d6d,0x3d55bd0e,0x3d35bd35,0xbd55bd0e,0xbcc43d6d,0x3d7b3c48,0x3d800000,0xbc48bd7b,0xbd6d3cc4,0x3d0e3d55,
0x3d353d35,0x3d0ebd55,0xbd6dbcc4,0xbc483d7b,0x80003d80,0x3d7bbc48,0xbcc4bd6d,0xbd553d0e,0xbd353d35,0x3d553d0e,0x3cc4bd6d,0xbd7bbc48,0xbd800000,0x3c483d7b,0x3d6dbcc4,0xbd0ebd55,
0x3d80,0x3d800000,0xbd80,0xbd800000,0x3d80,0x3d800000,0xbd80,0xbd800000,0x3d80,0x3d800000,0xbd80,0xbd800000,0x3d80,0x3d800000,0xbd80,0xbd800000,
0x3d80,0x3d800000,0xbd80,0xbd800000,0x3d80,0x3d800000,0xbd80,0xbd800000,0x3d80,0x3d800000,0xbd80,0xbd800000,0x3d80,0x3d800000,0xbd80,0xbd800000,
0xbd353d35,0x3d0e3d55,0x3d6dbcc4,0xbc48bd7b,0x3d80,0x3d7b3c48,0x3cc4bd6d,0xbd55bd0e,0xbd35bd35,0xbd553d0e,0x3cc43d6d,0x3d7bbc48,0xbd800000,0xbc483d7b,0x3d6d3cc4,0x3d0ebd55,
0x3d35bd35,0xbd0ebd55,0xbd6d3cc4,0x3c483d7b,0xbd80,0xbd7bbc48,0xbcc43d6d,0x3d553d0e,0x3d353d35,0x3d55bd0e,0xbcc4bd6d,0xbd7b3c48,0x3d800000,0x3c48bd7b,0xbd6dbcc4,0xbd0e3d55,
0xbd80,0xbd6dbcc4,0xbd353d35,0x3cc43d6d,0x3d800000,0x3cc4bd6d,0xbd35bd35,0xbd6d3cc4,0x3d80,0x3d6d3cc4,0x3d35bd35,0xbcc4bd6d,0xbd800000,0xbcc43d6d,0x3d353d35,0x3d6dbcc4,
0xbd80,0xbd6dbcc4,0xbd353d35,0x3cc43d6d,0x3d800000,0x3cc4bd6d,0xbd35bd35,0xbd6d3cc4,0x3d80,0x3d6d3cc4,0x3d35bd35,0xbcc4bd6d,0xbd800000,0xbcc43d6d,0x3d353d35,0x3d6dbcc4,
0xbd353d35,0x3c483d7b,0x3d6d3cc4,0x3d55bd0e,0x3d800000,0x3d0ebd55,0xbcc4bd6d,0xbd7bbc48,0xbd35bd35,0xbd7b3c48,0xbcc43d6d,0x3d0e3d55,0x3d80,0x3d553d0e,0x3d6dbcc4,0x3c48bd7b,
0x3d35bd35,0xbc48bd7b,0xbd6dbcc4,0xbd553d0e,0xbd800000,0xbd0e3d55,0x3cc43d6d,0x3d7b3c48,0x3d353d35,0x3d7bbc48,0x3cc4bd6d,0xbd0ebd55,0xbd80,0xbd55bd0e,0xbd6d3cc4,0xbc483d7b,
0x3d80,0x3d353d35,0x3d800000,0x3d35bd35,0xbd80,0xbd35bd35,0xbd800000,0xbd353d35,0x3d80,0x3d353d35,0x3d800000,0x3d35bd35,0xbd80,0xbd35bd35,0xbd800000,0xbd353d35,
0x3d80,0x3d353d35,0x3d800000,0x3d35bd35,0xbd80,0xbd35bd35,0xbd800000,0xbd353d35,0x3d80,0x3d353d35,0x3d800000,0x3d35bd35,0xbd80,0xbd35bd35,0xbd800000,0xbd353d35,
0xbd353d35,0xbc483d7b,0x3cc43d6d,0x3d553d0e,0xbd80,0xbd0ebd55,0xbd6dbcc4,0xbd7b3c48,0xbd35bd35,0xbd7bbc48,0xbd6d3cc4,0xbd0e3d55,0x3d800000,0x3d55bd0e,0x3cc4bd6d,0xbc48bd7b,
0x3d35bd35,0x3c48bd7b,0xbcc4bd6d,0xbd55bd0e,0x3d80,0x3d0e3d55,0x3d6d3cc4,0x3d7bbc48,0x3d353d35,0x3d7b3c48,0x3d6dbcc4,0x3d0ebd55,0xbd800000,0xbd553d0e,0xbcc43d6d,0x3c483d7b,
0xbd80,0xbcc4bd6d,0xbd35bd35,0xbd6dbcc4,0xbd800000,0xbd6d3cc4,0xbd353d35,0xbcc43d6d,0x3d80,0x3cc43d6d,0x3d353d35,0x3d6d3cc4,0x3d800000,0x3d6dbcc4,0x3d35bd35,0x3cc4bd6d,
0xbd80,0xbcc4bd6d,0xbd35bd35,0xbd6dbcc4,0xbd800000,0xbd6d3cc4,0xbd353d35,0xbcc43d6d,0x3d80,0x3cc43d6d,0x3d353d35,0x3d6d3cc4,0x3d800000,0x3d6dbcc4,0x3d35bd35,0x3cc4bd6d,
0xbd353d35,0xbd0e3d55,0xbcc43d6d,0xbc483d7b,0xbd800000,0xbd7b3c48,0xbd6d3cc4,0xbd553d0e,0xbd35bd35,0xbd55bd0e,0xbd6dbcc4,0xbd7bbc48,0xbd80,0xbc48bd7b,0xbcc4bd6d,0xbd0ebd55,
0x3d35bd35,0x3d0ebd55,0x3cc4bd6d,0x3c48bd7b,0x3d800000,0x3d7bbc48,0x3d6dbcc4,0x3d55bd0e,0x3d353d35,0x3d553d0e,0x3d6d3cc4,0x3d7b3c48,0x3d80,0x3c483d7b,0x3cc43d6d,0x3d0e3d55,
0xbd800000,0x80003d80,0x3d800000,0x8000bd80,0xbd800000,0x80003d80,0x3d800000,0x8000bd80,0xbd800000,0x80003d80,0x3d800000,0x8000bd80,0xbd800000,0x80003d80,0x3d800000,0x8000bd80,
0xbd800000,0x80003d80,0x3d800000,0x8000bd80,0xbd800000,0x80003d80,0x3d800000,0x8000bd80,0xbd800000,0x80003d80,0x3d800000,0x8000bd80,0xbd800000,0x80003d80,0x3d800000,0x8000bd80,
0xbd35bd35,0xbd553d0e,0x3cc43d6d,0x3d7bbc48,0xbd800000,0xbc483d7b,0x3d6d3cc4,0x3d0ebd55,0x3d35bd35,0xbd0ebd55,0xbd6d3cc4,0x3c483d7b,0x8000bd80,0xbd7bbc48,0xbcc43d6d,0x3d553d0e,
0x3d353d35,0x3d55bd0e,0xbcc4bd6d,0xbd7b3c48,0x3d800000,0x3c48bd7b,0xbd6dbcc4,0xbd0e3d55,0xbd353d35,0x3d0e3d55,0x3d6dbcc4,0xbc48bd7b,0x80003d80,0x3d7b3c48,0x3cc4bd6d,0xbd55bd0e,
0x3d800000,0x3cc4bd6d,0xbd35bd35,0xbd6d3cc4,0x80003d80,0x3d6d3cc4,0x3d35bd35,0xbcc4bd6d,0xbd800000,0xbcc43d6d,0x3d353d35,0x3d6dbcc4,0x8000bd80,0xbd6dbcc4,0xbd353d35,0x3cc43d6d,
0x3d800000,0x3cc4bd6d,0xbd35bd35,0xbd6d3cc4,0x80003d80,0x3d6d3cc4,0x3d35bd35,0xbcc4bd6d,0xbd800000,0xbcc43d6d,0x3d353d35,0x3d6dbcc4,0x8000bd80,0xbd6dbcc4,0xbd353d35,0x3cc43d6d,
0xbd35bd35,0xbd7b3c48,0xbcc43d6d,0x3d0e3d55,0x80003d80,0x3d553d0e,0x3d6dbcc4,0x3c48bd7b,0x3d35bd35,0xbc48bd7b,0xbd6dbcc4,0xbd553d0e,0xbd800000,0xbd0e3d55,0x3cc43d6d,0x3d7b3c48,
0x3d353d35,0x3d7bbc48,0x3cc4bd6d,0xbd0ebd55,0x8000bd80,0xbd55bd0e,0xbd6d3cc4,0xbc483d7b,0xbd353d35,0x3c483d7b,0x3d6d3cc4,0x3d55bd0e,0x3d800000,0x3d0ebd55,0xbcc4bd6d,0xbd7bbc48,
0xbd800000,0xbd353d35,0x80003d80,0x3d353d35,0x3d800000,0x3d35bd35,0x8000bd80,0xbd35bd35,0xbd800000,0xbd353d35,0x80003d80,0x3d353d35,0x3d800000,0x3d35bd35,0x8000bd80,0xbd35bd35,
0xbd800000,0xbd353d35,0x80003d80,0x3d353d35,0x3d800000,0x3d35bd35,0x8000bd80,0xbd35bd35,0xbd800000,0xbd353d35,0x80003d80,0x3d353d35,0x3d800000,0x3d35bd35,0x8000bd80,0xbd35bd35,
0xbd35bd35,0xbd7bbc48,0xbd6d3cc4,0xbd0e3d55,0x3d800000,0x3d55bd0e,0x3cc4bd6d,0xbc48bd7b,0x3d35bd35,0x3c48bd7b,0xbcc4bd6d,0xbd55bd0e,0x80003d80,0x3d0e3d55,0x3d6d3cc4,0x3d7bbc48,
0x3d353d35,0x3d7b3c48,0x3d6dbcc4,0x3d0ebd55,0xbd800000,0xbd553d0e,0xbcc43d6d,0x3c483d7b,0xbd353d35,0xbc483d7b,0x3cc43d6d,0x3d553d0e,0x8000bd80,0xbd0ebd55,0xbd6dbcc4,0xbd7b3c48,
0x3d800000,0x3d6dbcc4,0x3d35bd35,0x3cc4bd6d,0x8000bd80,0xbcc4bd6d,0xbd35bd35,0xbd6dbcc4,0xbd800000,0xbd6d3cc4,0xbd353d35,0xbcc43d6d,0x80003d80,0x3cc43d6d,0x3d353d35,0x3d6d3cc4,
0x3d800000,0x3d6dbcc4,0x3d35bd35,0x3cc4bd6d,0x8000bd80,0xbcc4bd6d,0xbd35bd35,0xbd6dbcc4,0xbd800000,0xbd6d3cc4,0xbd353d35,0xbcc43d6d,0x80003d80,0x3cc43d6d,0x3d353d35,0x3d6d3cc4,
0xbd35bd35,0xbd55bd0e,0xbd6dbcc4,0xbd7bbc48,0x8000bd80,0xbc48bd7b,0xbcc4bd6d,0xbd0ebd55,0x3d35bd35,0x3d0ebd55,0x3cc4bd6d,0x3c48bd7b,0x3d800000,0x3d7bbc48,0x3d6dbcc4,0x3d55bd0e,
0x3d353d35,0x3d553d0e,0x3d6d3cc4,0x3d7b3c48,0x80003d80,0x3c483d7b,0x3cc43d6d,0x3d0e3d55,0xbd353d35,0xbd0e3d55,0xbcc43d6d,0xbc483d7b,0xbd800000,0xbd7b3c48,0xbd6d3cc4,0xbd553d0e,
0x3d80,0xbb493d80,0xbbc93d7f,0xbc163d7d,0xbc483d7b,0xbc793d78,0xbc953d75,0xbcac3d71,0xbcc43d6d,0xbcdb3d67,0xbcf13d62,0xbd043d5c,0xbd0e3d55,0xbd183d4e,0xbd223d46,0xbd2c3d3e,
0xbd353d35,0xbd3e3d2c,0xbd463d22,0xbd4e3d18,0xbd553d0e,0xbd5c3d04,0xbd623cf1,0xbd673cdb,0xbd6d3cc4,0xbd713cac,0xbd753c95,0xbd783c79,0xbd7b3c48,0xbd7d3c16,0xbd7f3bc9,0xbd803b49,
0xbd553d0e,0xbd713cac,0xbd7f3bc9,0xbd7dbc16,0x3d80,0xbc793d78,0xbcf13d62,0xbd2c3d3e,0xbc48bd7b,0x3b49bd80,0x3c95bd75,0x3d04bd5c,0xbd6dbcc4,0xbd4ebd18,0xbd22bd46,0xbcdbbd67,
0x3d7b3c48,0x3d673cdb,0x3d463d22,0x3d183d4e,0x3d35bd35,0x3d5cbd04,0x3d75bc95,0x3d80bb49,0xbd0e3d55,0xbd3e3d2c,0xbd623cf1,0xbd783c79,0x3cc43d6d,0x3c163d7d,0xbbc93d7f,0xbcac3d71,
0x3cc4bd6d,0x3d3ebd2c,0x3d75bc95,0x3d7d3c16,0x3d553d0e,0x3d043d5c,0x3bc93d7f,0xbcac3d71,0x3d80,0xbcdb3d67,0xbd463d22,0xbd783c79,0xbd7bbc48,0xbd4ebd18,0xbcf1bd62,0xbb49bd80,
0x3d6dbcc4,0x3d803b49,0x3d623cf1,0x3d183d4e,0x3c483d7b,0xbc793d78,0xbd223d46,0xbd673cdb,0xbd353d35,0xbd713cac,0xbd7fbbc9,0xbd5cbd04,0xbd0ebd55,0xbc16bd7d,0x3c95bd75,0x3d2cbd3e,
0xbd7b3c48,0xbd67bcdb,0xbcf1bd62,0x3c16bd7d,0x3d6d3cc4,0x3d043d5c,0xbbc93d7f,0xbd2c3d3e,0xbd0ebd55,0x3b49bd80,0x3d22bd46,0x3d78bc79,0x3d80,0xbd183d4e,0xbd753c95,0xbd71bcac,
0x3d553d0e,0x3cac3d71,0xbc953d75,0xbd4e3d18,0xbcc4bd6d,0x3c79bd78,0x3d46bd22,0x3d80bb49,0xbc483d7b,0xbd3e3d2c,0xbd7f3bc9,0xbd5cbd04,0x3d35bd35,0x3d7dbc16,0x3d623cf1,0x3cdb3d67,
0xbd353d35,0xbd80bb49,0xbd22bd46,0x3c16bd7d,0x3d55bd0e,0x3d783c79,0x3cf13d62,0xbcac3d71,0xbd6d3cc4,0xbd67bcdb,0xbc95bd75,0x3d04bd5c,0x3d7bbc48,0x3d4e3d18,0x3bc93d7f,0xbd2c3d3e,
0x3d80,0xbd3e3d2c,0xbd7fbbc9,0xbd18bd4e,0x3c48bd7b,0x3d5cbd04,0x3d753c95,0x3cdb3d67,0xbcc43d6d,0xbd713cac,0xbd62bcf1,0xbc79bd78,0x3d0ebd55,0x3d7dbc16,0x3d463d22,0x3b493d80,
0xbd7bbc48,0xbcacbd71,0x3d22bd46,0x3d7d3c16,0x3d35bd35,0x3d783c79,0x3c953d75,0xbd2c3d3e,0x3d0ebd55,0x3d803b49,0x3cf13d62,0xbd043d5c,0x3cc43d6d,0xbd183d4e,0xbd7fbbc9,0xbcdbbd67,
0x3d55bd0e,0x3d673cdb,0x3bc93d7f,0xbd4e3d18,0x3d80,0xbd5c3d04,0xbd62bcf1,0xbb49bd80,0x3c483d7b,0xbd3e3d2c,0xbd75bc95,0xbc79bd78,0xbd6dbcc4,0xbc16bd7d,0x3d46bd22,0x3d713cac,
0x3d6dbcc4,0x3d2c3d3e,0xbcf13d62,0xbd7dbc16,0xbc48bd7b,0x3d5cbd04,0x3d463d22,0xbcac3d71,0xbd353d35,0xbd67bcdb,0x3bc9bd7f,0x3d78bc79,0x3d0e3d55,0xbd183d4e,0xbd75bc95,0xbb49bd80,
0x3cc4bd6d,0x3d803b49,0x3c953d75,0xbd4e3d18,0xbd55bd0e,0x3c79bd78,0x3d7fbbc9,0x3cdb3d67,0x3d80,0xbd713cac,0xbd22bd46,0x3d04bd5c,0x3d7b3c48,0x3c163d7d,0xbd623cf1,0xbd3ebd2c,
0xbd55bd0e,0x3cdbbd67,0x3d753c95,0xbc163d7d,0xbcc4bd6d,0x3d5cbd04,0x3d223d46,0xbd2c3d3e,0x3c48bd7b,0x3d803b49,0x3bc93d7f,0xbd783c79,0x3d35bd35,0x3d4e3d18,0xbcf13d62,0xbd71bcac,
0x3d7bbc48,0x3cac3d71,0xbd623cf1,0xbd18bd4e,0x3d6d3cc4,0xbc793d78,0xbd7fbbc9,0xbb49bd80,0x3d0e3d55,0xbd3e3d2c,0xbd46bd22,0x3d04bd5c,0x3d80,0xbd7d3c16,0xbc95bd75,0x3d67bcdb,
0xbd800000,0xbd80bb49,0xbd7fbbc9,0xbd7dbc16,0xbd7bbc48,0xbd78bc79,0xbd75bc95,0xbd71bcac,0xbd6dbcc4,0xbd67bcdb,0xbd62bcf1,0xbd5cbd04,0xbd55bd0e,0xbd4ebd18,0xbd46bd22,0xbd3ebd2c,
0xbd35bd35,0xbd2cbd3e,0xbd22bd46,0xbd18bd4e,0xbd0ebd55,0xbd04bd5c,0xbcf1bd62,0xbcdbbd67,0xbcc4bd6d,0xbcacbd71,0xbc95bd75,0xbc79bd78,0xbc48bd7b,0xbc16bd7d,0xbbc9bd7f,0xbb49bd80,
0xbd0ebd55,0xbcacbd71,0xbbc9bd7f,0x3c16bd7d,0xbd800000,0xbd78bc79,0xbd62bcf1,0xbd3ebd2c,0x3d7bbc48,0x3d803b49,0x3d753c95,0x3d5c3d04,0x3cc4bd6d,0x3d18bd4e,0x3d46bd22,0x3d67bcdb,
0xbc483d7b,0xbcdb3d67,0xbd223d46,0xbd4e3d18,0x3d353d35,0x3d043d5c,0x3c953d75,0x3b493d80,0xbd55bd0e,0xbd2cbd3e,0xbcf1bd62,0xbc79bd78,0xbd6d3cc4,0xbd7d3c16,0xbd7fbbc9,0xbd71bcac,
0x3d6d3cc4,0x3d2c3d3e,0x3c953d75,0xbc163d7d,0xbd0e3d55,0xbd5c3d04,0xbd7f3bc9,0xbd71bcac,0xbd800000,0xbd67bcdb,0xbd22bd46,0xbc79bd78,0x3c48bd7b,0x3d18bd4e,0x3d62bcf1,0x3d80bb49,
0x3cc43d6d,0xbb493d80,0xbcf13d62,0xbd4e3d18,0xbd7b3c48,0xbd78bc79,0xbd46bd22,0xbcdbbd67,0xbd35bd35,0xbcacbd71,0x3bc9bd7f,0x3d04bd5c,0x3d55bd0e,0x3d7dbc16,0x3d753c95,0x3d3e3d2c,
0xbc48bd7b,0x3cdbbd67,0x3d62bcf1,0x3d7d3c16,0xbcc43d6d,0xbd5c3d04,0xbd7fbbc9,0xbd3ebd2c,0x3d55bd0e,0x3d803b49,0x3d463d22,0x3c793d78,0xbd800000,0xbd4ebd18,0xbc95bd75,0x3cacbd71,
0xbd0e3d55,0xbd713cac,0xbd75bc95,0xbd18bd4e,0x3d6dbcc4,0x3d783c79,0x3d223d46,0x3b493d80,0xbd7bbc48,0xbd2cbd3e,0xbbc9bd7f,0x3d04bd5c,0x3d353d35,0x3c163d7d,0xbcf13d62,0xbd673cdb,
0xbd35bd35,0x3b49bd80,0x3d46bd22,0x3d7d3c16,0x3d0e3d55,0xbc793d78,0xbd623cf1,0xbd71bcac,0xbcc4bd6d,0x3cdbbd67,0x3d75bc95,0x3d5c3d04,0x3c483d7b,0xbd183d4e,0xbd7f3bc9,0xbd3ebd2c,
0xbd800000,0xbd2cbd3e,0x3bc9bd7f,0x3d4ebd18,0x3d7b3c48,0x3d043d5c,0xbc953d75,0xbd673cdb,0xbd6dbcc4,0xbcacbd71,0x3cf1bd62,0x3d78bc79,0x3d553d0e,0x3c163d7d,0xbd223d46,0xbd803b49,
0x3c48bd7b,0x3d71bcac,0x3d463d22,0xbc163d7d,0x3d353d35,0xbc793d78,0xbd753c95,0xbd3ebd2c,0x3d553d0e,0xbb493d80,0xbd623cf1,0xbd5cbd04,0xbd6d3cc4,0xbd4ebd18,0x3bc9bd7f,0x3d67bcdb,
0x3d0e3d55,0xbcdb3d67,0xbd7f3bc9,0xbd18bd4e,0xbd800000,0xbd04bd5c,0x3cf1bd62,0x3d80bb49,0xbd7b3c48,0xbd2cbd3e,0x3c95bd75,0x3d78bc79,0x3cc4bd6d,0x3d7dbc16,0x3d223d46,0xbcac3d71,
0x3cc43d6d,0xbd3e3d2c,0xbd62bcf1,0x3c16bd7d,0x3d7bbc48,0x3d043d5c,0xbd223d46,0xbd71bcac,0xbd35bd35,0x3cdbbd67,0x3d7f3bc9,0x3c793d78,0xbd553d0e,0xbd4ebd18,0x3c95bd75,0x3d80bb49,
0x3d6d3cc4,0xbb493d80,0xbd753c95,0xbd18bd4e,0x3d0ebd55,0x3d783c79,0x3bc93d7f,0xbd673cdb,0xbd800000,0xbcacbd71,0x3d46bd22,0x3d5c3d04,0xbc483d7b,0xbd7d3c16,0xbcf1bd62,0x3d2cbd3e,
0x3d0ebd55,0x3d673cdb,0xbc953d75,0xbd7dbc16,0x3d6dbcc4,0x3d043d5c,0xbd463d22,0xbd3ebd2c,0x3d7b3c48,0xbb493d80,0xbd7f3bc9,0xbc79bd78,0x3d353d35,0xbd183d4e,0xbd62bcf1,0x3cacbd71,
0x3c483d7b,0xbd713cac,0xbcf1bd62,0x3d4ebd18,0xbcc43d6d,0xbd78bc79,0x3bc9bd7f,0x3d80bb49,0xbd553d0e,0xbd2cbd3e,0x3d22bd46,0x3d5c3d04,0xbd800000,0xbc16bd7d,0x3d75bc95,0x3cdb3d67,
0x3d80,0xbd80bb49,0x3bc9bd7f,0x3d7d3c16,0xbc483d7b,0xbd78bc79,0x3c95bd75,0x3d713cac,0xbcc43d6d,0xbd67bcdb,0x3cf1bd62,0x3d5c3d04,0xbd0e3d55,0xbd4ebd18,0x3d22bd46,0x3d3e3d2c,
0xbd353d35,0xbd2cbd3e,0x3d46bd22,0x3d183d4e,0xbd553d0e,0xbd04bd5c,0x3d62bcf1,0x3cdb3d67,0xbd6d3cc4,0xbcacbd71,0x3d75bc95,0x3c793d78,0xbd7b3c48,0xbc16bd7d,0x3d7fbbc9,0x3b493d80,
0xbd553d0e,0xbcacbd71,0x3d7fbbc9,0xbc163d7d,0x3d80,0xbd78bc79,0x3cf1bd62,0x3d3e3d2c,0xbc48bd7b,0x3d803b49,0xbc953d75,0xbd5cbd04,0xbd6dbcc4,0x3d18bd4e,0x3d223d46,0xbd673cdb,
0x3d7b3c48,0xbcdb3d67,0xbd46bd22,0x3d4ebd18,0x3d35bd35,0x3d043d5c,0xbd753c95,0xbb49bd80,0xbd0e3d55,0xbd2cbd3e,0x3d62bcf1,0x3c793d78,0x3cc43d6d,0xbd7d3c16,0x3bc9bd7f,0x3d713cac,
0x3cc4bd6d,0x3d2c3d3e,0xbd753c95,0x3c16bd7d,0x3d553d0e,0xbd5c3d04,0xbbc9bd7f,0x3d713cac,0x3d80,0xbd67bcdb,0x3d46bd22,0x3c793d78,0xbd7bbc48,0x3d18bd4e,0x3cf13d62,0xbd803b49,
0x3d6dbcc4,0xbb493d80,0xbd62bcf1,0x3d4ebd18,0x3c483d7b,0xbd78bc79,0x3d22bd46,0x3cdb3d67,0xbd353d35,0xbcacbd71,0x3d7f3bc9,0xbd043d5c,0xbd0ebd55,0x3d7dbc16,0xbc953d75,0xbd3ebd2c,
0xbd7b3c48,0x3cdbbd67,0x3cf13d62,0xbd7dbc16,0x3d6d3cc4,0xbd5c3d04,0x3bc9bd7f,0x3d3e3d2c,0xbd0ebd55,0x3d803b49,0xbd223d46,0xbc79bd78,0x3d80,0xbd4ebd18,0x3d75bc95,0xbcac3d71,
0x3d553d0e,0xbd713cac,0x3c95bd75,0x3d183d4e,0xbcc4bd6d,0x3d783c79,0xbd463d22,0xbb49bd80,0xbc483d7b,0xbd2cbd3e,0x3d7fbbc9,0xbd043d5c,0x3d35bd35,0x3c163d7d,0xbd62bcf1,0x3d67bcdb,
0xbd353d35,0x3b49bd80,0x3d223d46,0xbd7dbc16,0x3d55bd0e,0xbc793d78,0xbcf1bd62,0x3d713cac,0xbd6d3cc4,0x3cdbbd67,0x3c953d75,0xbd5cbd04,0x3d7bbc48,0xbd183d4e,0xbbc9bd7f,0x3d3e3d2c,
0x3d80,0xbd2cbd3e,0x3d7f3bc9,0xbd4e3d18,0x3c48bd7b,0x3d043d5c,0xbd75bc95,0x3d67bcdb,0xbcc43d6d,0xbcacbd71,0x3d623cf1,0xbd783c79,0x3d0ebd55,0x3c163d7d,0xbd46bd22,0x3d80bb49,
0xbd7bbc48,0x3d71bcac,0xbd223d46,0x3c16bd7d,0x3d35bd35,0xbc793d78,0xbc95bd75,0x3d3e3d2c,0x3d0ebd55,0xbb493d80,0xbcf1bd62,0x3d5c3d04,0x3cc43d6d,0xbd4ebd18,0x3d7f3bc9,0xbd673cdb,
0x3d55bd0e,0xbcdb3d67,0xbbc9bd7f,0x3d183d4e,0x3d80,0xbd04bd5c,0x3d623cf1,0xbd803b49,0x3c483d7b,0xbd2cbd3e,0x3d753c95,0xbd783c79,0xbd6dbcc4,0x3d7dbc16,0xbd463d22,0x3cacbd71,
0x3d6dbcc4,0xbd3e3d2c,0x3cf1bd62,0xbc163d7d,0xbc48bd7b,0x3d043d5c,0xbd46bd22,0x3d713cac,0xbd353d35,0x3cdbbd67,0xbbc93d7f,0xbc79bd78,0x3d0e3d55,0xbd4ebd18,0x3d753c95,0xbd803b49,
0x3cc4bd6d,0xbb493d80,0xbc95bd75,0x3d183d4e,0xbd55bd0e,0x3d783c79,0xbd7f3bc9,0x3d67bcdb,0x3d80,0xbcacbd71,0x3d223d46,0xbd5cbd04,0x3d7b3c48,0xbd7d3c16,0x3d62bcf1,0xbd2c3d3e,
0xbd55bd0e,0x3d673cdb,0xbd75bc95,0x3d7d3c16,0xbcc4bd6d,0x3d043d5c,0xbd22bd46,0x3d3e3d2c,0x3c48bd7b,0xbb493d80,0xbbc9bd7f,0x3c793d78,0x3d35bd35,0xbd183d4e,0x3cf1bd62,0xbcac3d71,
0x3d7bbc48,0xbd713cac,0x3d62bcf1,0xbd4e3d18,0x3d6d3cc4,0xbd78bc79,0x3d7f3bc9,0xbd803b49,0x3d0e3d55,0xbd2cbd3e,0x3d463d22,0xbd5cbd04,0x3d80,0xbc16bd7d,0x3c953d75,0xbcdbbd67,
0xbd800000,0x3b49bd80,0x3d7f3bc9,0xbc163d7d,0xbd7bbc48,0x3c79bd78,0x3d753c95,0xbcac3d71,0xbd6dbcc4,0x3cdbbd67,0x3d623cf1,0xbd043d5c,0xbd55bd0e,0x3d18bd4e,0x3d463d22,0xbd2c3d3e,
0xbd35bd35,0x3d3ebd2c,0x3d223d46,0xbd4e3d18,0xbd0ebd55,0x3d5cbd04,0x3cf13d62,0xbd673cdb,0xbcc4bd6d,0x3d71bcac,0x3c953d75,0xbd783c79,0xbc48bd7b,0x3d7dbc16,0x3bc93d7f,0xbd803b49,
0xbd0ebd55,0x3d71bcac,0x3bc93d7f,0xbd7dbc16,0xbd800000,0x3c79bd78,0x3d623cf1,0xbd2c3d3e,0x3d7bbc48,0xbb493d80,0xbd75bc95,0x3d04bd5c,0x3cc4bd6d,0x3d4e3d18,0xbd463d22,0xbcdbbd67,
0xbc483d7b,0xbd67bcdb,0x3d22bd46,0x3d183d4e,0x3d353d35,0xbd5c3d04,0xbc95bd75,0x3d80bb49,0xbd55bd0e,0x3d3ebd2c,0x3cf13d62,0xbd783c79,0xbd6d3cc4,0xbc16bd7d,0x3d7f3bc9,0xbcac3d71,
0x3d6d3cc4,0xbd3e3d2c,0xbc95bd75,0x3d7d3c16,0xbd0e3d55,0xbd04bd5c,0x3d7fbbc9,0xbcac3d71,0xbd800000,0x3cdbbd67,0x3d223d46,0xbd783c79,0x3c48bd7b,0x3d4e3d18,0xbd623cf1,0xbb49bd80,
0x3cc43d6d,0xbd80bb49,0x3cf1bd62,0x3d183d4e,0xbd7b3c48,0x3c79bd78,0x3d463d22,0xbd673cdb,0xbd35bd35,0x3d71bcac,0xbbc93d7f,0xbd5cbd04,0x3d55bd0e,0x3c163d7d,0xbd75bc95,0x3d2cbd3e,
0xbc48bd7b,0x3d673cdb,0xbd623cf1,0x3c16bd7d,0xbcc43d6d,0xbd04bd5c,0x3d7f3bc9,0xbd2c3d3e,0x3d55bd0e,0xbb493d80,0xbd46bd22,0x3d78bc79,0xbd800000,0x3d18bd4e,0x3c953d75,0xbd71bcac,
0xbd0e3d55,0xbcacbd71,0x3d753c95,0xbd4e3d18,0x3d6dbcc4,0xbc793d78,0xbd22bd46,0x3d80bb49,0xbd7bbc48,0x3d3ebd2c,0x3bc93d7f,0xbd5cbd04,0x3d353d35,0xbd7d3c16,0x3cf1bd62,0x3cdb3d67,
0xbd35bd35,0x3d803b49,0xbd463d22,0x3c16bd7d,0x3d0e3d55,0xbd78bc79,0x3d62bcf1,0xbcac3d71,0xbcc4bd6d,0x3d673cdb,0xbd753c95,0x3d04bd5c,0x3c483d7b,0xbd4ebd18,0x3d7fbbc9,0xbd2c3d3e,
0xbd800000,0x3d3ebd2c,0xbbc93d7f,0xbd18bd4e,0x3d7b3c48,0xbd5c3d04,0x3c95bd75,0x3cdb3d67,0xbd6dbcc4,0x3d71bcac,0xbcf13d62,0xbc79bd78,0x3d553d0e,0xbd7d3c16,0x3d22bd46,0x3b493d80,
0x3c48bd7b,0x3cac3d71,0xbd46bd22,0x3d7d3c16,0x3d353d35,0xbd78bc79,0x3d75bc95,0xbd2c3d3e,0x3d553d0e,0xbd80bb49,0x3d62bcf1,0xbd043d5c,0xbd6d3cc4,0x3d18bd4e,0xbbc93d7f,0xbcdbbd67,
0x3d0e3d55,0xbd67bcdb,0x3d7fbbc9,0xbd4e3d18,0xbd800000,0x3d5cbd04,0xbcf13d62,0xbb49bd80,0xbd7b3c48,0x3d3ebd2c,0xbc953d75,0xbc79bd78,0x3cc4bd6d,0x3c163d7d,0xbd22bd46,0x3d713cac,
0x3cc43d6d,0xbd2cbd3e,0x3d623cf1,0xbd7dbc16,0x3d7bbc48,0xbd5c3d04,0x3d22bd46,0xbcac3d71,0xbd35bd35,0x3d673cdb,0xbd7fbbc9,0x3d78bc79,0xbd553d0e,0x3d18bd4e,0xbc953d75,0xbb49bd80,
0x3d6d3cc4,0xbd80bb49,0x3d75bc95,0xbd4e3d18,0x3d0ebd55,0xbc793d78,0xbbc9bd7f,0x3cdb3d67,0xbd800000,0x3d71bcac,0xbd463d22,0x3d04bd5c,0xbc483d7b,0xbc16bd7d,0x3cf13d62,0xbd3ebd2c,
0x3d0ebd55,0xbcdb3d67,0x3c95bd75,0xbc163d7d,0x3d6dbcc4,0xbd5c3d04,0x3d46bd22,0xbd2c3d3e,0x3d7b3c48,0xbd80bb49,0x3d7fbbc9,0xbd783c79,0x3d353d35,0xbd4ebd18,0x3d623cf1,0xbd71bcac,
0x3c483d7b,0xbcacbd71,0x3cf13d62,0xbd18bd4e,0xbcc43d6d,0x3c79bd78,0xbbc93d7f,0xbb49bd80,0xbd553d0e,0x3d3ebd2c,0xbd223d46,0x3d04bd5c,0xbd800000,0x3d7dbc16,0xbd753c95,0x3d67bcdb,
0x3d80,0x3b49bd80,0xbbc93d7f,0x3c16bd7d,0xbc483d7b,0x3c79bd78,0xbc953d75,0x3cacbd71,0xbcc43d6d,0x3cdbbd67,0xbcf13d62,0x3d04bd5c,0xbd0e3d55,0x3d18bd4e,0xbd223d46,0x3d2cbd3e,
0xbd353d35,0x3d3ebd2c,0xbd463d22,0x3d4ebd18,0xbd553d0e,0x3d5cbd04,0xbd623cf1,0x3d67bcdb,0xbd6d3cc4,0x3d71bcac,0xbd753c95,0x3d78bc79,0xbd7b3c48,0x3d7dbc16,0xbd7f3bc9,0x3d80bb49,
0xbd553d0e,0x3d71bcac,0xbd7f3bc9,0x3d7d3c16,0x3d80,0x3c79bd78,0xbcf13d62,0x3d2cbd3e,0xbc48bd7b,0xbb493d80,0x3c95bd75,0xbd043d5c,0xbd6dbcc4,0x3d4e3d18,0xbd22bd46,0x3cdb3d67,
0x3d7b3c48,0xbd67bcdb,0x3d463d22,0xbd18bd4e,0x3d35bd35,0xbd5c3d04,0x3d75bc95,0xbd803b49,0xbd0e3d55,0x3d3ebd2c,0xbd623cf1,0x3d78bc79,0x3cc43d6d,0xbc16bd7d,0xbbc93d7f,0x3cacbd71,
0x3cc4bd6d,0xbd3e3d2c,0x3d75bc95,0xbd7dbc16,0x3d553d0e,0xbd04bd5c,0x3bc93d7f,0x3cacbd71,0x3d80,0x3cdbbd67,0xbd463d22,0x3d78bc79,0xbd7bbc48,0x3d4e3d18,0xbcf1bd62,0x3b493d80,
0x3d6dbcc4,0xbd80bb49,0x3d623cf1,0xbd18bd4e,0x3c483d7b,0x3c79bd78,0xbd223d46,0x3d67bcdb,0xbd353d35,0x3d71bcac,0xbd7fbbc9,0x3d5c3d04,0xbd0ebd55,0x3c163d7d,0x3c95bd75,0xbd2c3d3e,
0xbd7b3c48,0x3d673cdb,0xbcf1bd62,0xbc163d7d,0x3d6d3cc4,0xbd04bd5c,0xbbc93d7f,0x3d2cbd3e,0xbd0ebd55,0xbb493d80,0x3d22bd46,0xbd783c79,0x3d80,0x3d18bd4e,0xbd753c95,0x3d713cac,
0x3d553d0e,0xbcacbd71,0xbc953d75,0x3d4ebd18,0xbcc4bd6d,0xbc793d78,0x3d46bd22,0xbd803b49,0xbc483d7b,0x3d3ebd2c,0xbd7f3bc9,0x3d5c3d04,0x3d35bd35,0xbd7d3c16,0x3d623cf1,0xbcdbbd67,
0xbd353d35,0x3d803b49,0xbd22bd46,0xbc163d7d,0x3d55bd0e,0xbd78bc79,0x3cf13d62,0x3cacbd71,0xbd6d3cc4,0x3d673cdb,0xbc95bd75,0xbd043d5c,0x3d7bbc48,0xbd4ebd18,0x3bc93d7f,0x3d2cbd3e,
0x3d80,0x3d3ebd2c,0xbd7fbbc9,0x3d183d4e,0x3c48bd7b,0xbd5c3d04,0x3d753c95,0xbcdbbd67,0xbcc43d6d,0x3d71bcac,0xbd62bcf1,0x3c793d78,0x3d0ebd55,0xbd7d3c16,0x3d463d22,0xbb49bd80,
0xbd7bbc48,0x3cac3d71,0x3d22bd46,0xbd7dbc16,0x3d35bd35,0xbd78bc79,0x3c953d75,0x3d2cbd3e,0x3d0ebd55,0xbd80bb49,0x3cf13d62,0x3d04bd5c,0x3cc43d6d,0x3d18bd4e,0xbd7fbbc9,0x3cdb3d67,
0x3d55bd0e,0xbd67bcdb,0x3bc93d7f,0x3d4ebd18,0x3d80,0x3d5cbd04,0xbd62bcf1,0x3b493d80,0x3c483d7b,0x3d3ebd2c,0xbd75bc95,0x3c793d78,0xbd6dbcc4,0x3c163d7d,0x3d46bd22,0xbd71bcac,
0x3d6dbcc4,0xbd2cbd3e,0xbcf13d62,0x3d7d3c16,0xbc48bd7b,0xbd5c3d04,0x3d463d22,0x3cacbd71,0xbd353d35,0x3d673cdb,0x3bc9bd7f,0xbd783c79,0x3d0e3d55,0x3d18bd4e,0xbd75bc95,0x3b493d80,
0x3cc4bd6d,0xbd80bb49,0x3c953d75,0x3d4ebd18,0xbd55bd0e,0xbc793d78,0x3d7fbbc9,0xbcdbbd67,0x3d80,0x3d71bcac,0xbd22bd46,0xbd043d5c,0x3d7b3c48,0xbc16bd7d,0xbd623cf1,0x3d3e3d2c,
0xbd55bd0e,0xbcdb3d67,0x3d753c95,0x3c16bd7d,0xbcc4bd6d,0xbd5c3d04,0x3d223d46,0x3d2cbd3e,0x3c48bd7b,0xbd80bb49,0x3bc93d7f,0x3d78bc79,0x3d35bd35,0xbd4ebd18,0xbcf13d62,0x3d713cac,
0x3d7bbc48,0xbcacbd71,0xbd623cf1,0x3d183d4e,0x3d6d3cc4,0x3c79bd78,0xbd7fbbc9,0x3b493d80,0x3d0e3d55,0x3d3ebd2c,0xbd46bd22,0xbd043d5c,0x3d80,0x3d7dbc16,0xbc95bd75,0xbd673cdb,
0xbd800000,0x3d803b49,0xbd7fbbc9,0x3d7d3c16,0xbd7bbc48,0x3d783c79,0xbd75bc95,0x3d713cac,0xbd6dbcc4,0x3d673cdb,0xbd62bcf1,0x3d5c3d04,0xbd55bd0e,0x3d4e3d18,0xbd46bd22,0x3d3e3d2c,
0xbd35bd35,0x3d2c3d3e,0xbd22bd46,0x3d183d4e,0xbd0ebd55,0x3d043d5c,0xbcf1bd62,0x3cdb3d67,0xbcc4bd6d,0x3cac3d71,0xbc95bd75,0x3c793d78,0xbc48bd7b,0x3c163d7d,0xbbc9bd7f,0x3b493d80,
0xbd0ebd55,0x3cac3d71,0xbbc9bd7f,0xbc163d7d,0xbd800000,0x3d783c79,0xbd62bcf1,0x3d3e3d2c,0x3d7bbc48,0xbd80bb49,0x3d753c95,0xbd5cbd04,0x3cc4bd6d,0xbd183d4e,0x3d46bd22,0xbd673cdb,
0xbc483d7b,0x3cdbbd67,0xbd223d46,0x3d4ebd18,0x3d353d35,0xbd04bd5c,0x3c953d75,0xbb49bd80,0xbd55bd0e,0x3d2c3d3e,0xbcf1bd62,0x3c793d78,0xbd6d3cc4,0x3d7dbc16,0xbd7fbbc9,0x3d713cac,
0x3d6d3cc4,0xbd2cbd3e,0x3c953d75,0x3c16bd7d,0xbd0e3d55,0x3d5cbd04,0xbd7f3bc9,0x3d713cac,0xbd800000,0x3d673cdb,0xbd22bd46,0x3c793d78,0x3c48bd7b,0xbd183d4e,0x3d62bcf1,0xbd803b49,
0x3cc43d6d,0x3b49bd80,0xbcf13d62,0x3d4ebd18,0xbd7b3c48,0x3d783c79,0xbd46bd22,0x3cdb3d67,0xbd35bd35,0x3cac3d71,0x3bc9bd7f,0xbd043d5c,0x3d55bd0e,0xbd7d3c16,0x3d753c95,0xbd3ebd2c,
0xbc48bd7b,0xbcdb3d67,0x3d62bcf1,0xbd7dbc16,0xbcc43d6d,0x3d5cbd04,0xbd7fbbc9,0x3d3e3d2c,0x3d55bd0e,0xbd80bb49,0x3d463d22,0xbc79bd78,0xbd800000,0x3d4e3d18,0xbc95bd75,0xbcac3d71,
0xbd0e3d55,0x3d71bcac,0xbd75bc95,0x3d183d4e,0x3d6dbcc4,0xbd78bc79,0x3d223d46,0xbb49bd80,0xbd7bbc48,0x3d2c3d3e,0xbbc9bd7f,0xbd043d5c,0x3d353d35,0xbc16bd7d,0xbcf13d62,0x3d67bcdb,
0xbd35bd35,0xbb493d80,0x3d46bd22,0xbd7dbc16,0x3d0e3d55,0x3c79bd78,0xbd623cf1,0x3d713cac,0xbcc4bd6d,0xbcdb3d67,0x3d75bc95,0xbd5cbd04,0x3c483d7b,0x3d18bd4e,0xbd7f3bc9,0x3d3e3d2c,
0xbd800000,0x3d2c3d3e,0x3bc9bd7f,0xbd4e3d18,0x3d7b3c48,0xbd04bd5c,0xbc953d75,0x3d67bcdb,0xbd6dbcc4,0x3cac3d71,0x3cf1bd62,0xbd783c79,0x3d553d0e,0xbc16bd7d,0xbd223d46,0x3d80bb49,
0x3c48bd7b,0xbd713cac,0x3d463d22,0x3c16bd7d,0x3d353d35,0x3c79bd78,0xbd753c95,0x3d3e3d2c,0x3d553d0e,0x3b49bd80,0xbd623cf1,0x3d5c3d04,0xbd6d3cc4,0x3d4e3d18,0x3bc9bd7f,0xbd673cdb,
0x3d0e3d55,0x3cdbbd67,0xbd7f3bc9,0x3d183d4e,0xbd800000,0x3d043d5c,0x3cf1bd62,0xbd803b49,0xbd7b3c48,0x3d2c3d3e,0x3c95bd75,0xbd783c79,0x3cc4bd6d,0xbd7d3c16,0x3d223d46,0x3cacbd71,
0x3cc43d6d,0x3d3ebd2c,0xbd62bcf1,0xbc163d7d,0x3d7bbc48,0xbd04bd5c,0xbd223d46,0x3d713cac,0xbd35bd35,0xbcdb3d67,0x3d7f3bc9,0xbc79bd78,0xbd553d0e,0x3d4e3d18,0x3c95bd75,0xbd803b49,
0x3d6d3cc4,0x3b49bd80,0xbd753c95,0x3d183d4e,0x3d0ebd55,0xbd78bc79,0x3bc93d7f,0x3d67bcdb,0xbd800000,0x3cac3d71,0x3d46bd22,0xbd5cbd04,0xbc483d7b,0x3d7dbc16,0xbcf1bd62,0xbd2c3d3e,
0x3d0ebd55,0xbd67bcdb,0xbc953d75,0x3d7d3c16,0x3d6dbcc4,0xbd04bd5c,0xbd463d22,0x3d3e3d2c,0x3d7b3c48,0x3b49bd80,0xbd7f3bc9,0x3c793d78,0x3d353d35,0x3d18bd4e,0xbd62bcf1,0xbcac3d71,
0x3c483d7b,0x3d71bcac,0xbcf1bd62,0xbd4e3d18,0xbcc43d6d,0x3d783c79,0x3bc9bd7f,0xbd803b49,0xbd553d0e,0x3d2c3d3e,0x3d22bd46,0xbd5cbd04,0xbd800000,0x3c163d7d,0x3d75bc95,0xbcdbbd67,
0x3d80,0x3d803b49,0x3bc9bd7f,0xbd7dbc16,0xbc483d7b,0x3d783c79,0x3c95bd75,0xbd71bcac,0xbcc43d6d,0x3d673cdb,0x3cf1bd62,0xbd5cbd04,0xbd0e3d55,0x3d4e3d18,0x3d22bd46,0xbd3ebd2c,
0xbd353d35,0x3d2c3d3e,0x3d46bd22,0xbd18bd4e,0xbd553d0e,0x3d043d5c,0x3d62bcf1,0xbcdbbd67,0xbd6d3cc4,0x3cac3d71,0x3d75bc95,0xbc79bd78,0xbd7b3c48,0x3c163d7d,0x3d7fbbc9,0xbb49bd80,
0xbd553d0e,0x3cac3d71,0x3d7fbbc9,0x3c16bd7d,0x3d80,0x3d783c79,0x3cf1bd62,0xbd3ebd2c,0xbc48bd7b,0xbd80bb49,0xbc953d75,0x3d5c3d04,0xbd6dbcc4,0xbd183d4e,0x3d223d46,0x3d67bcdb,
0x3d7b3c48,0x3cdbbd67,0xbd46bd22,0xbd4e3d18,0x3d35bd35,0xbd04bd5c,0xbd753c95,0x3b493d80,0xbd0e3d55,0x3d2c3d3e,0x3d62bcf1,0xbc79bd78,0x3cc43d6d,0x3d7dbc16,0x3bc9bd7f,0xbd71bcac,
0x3cc4bd6d,0xbd2cbd3e,0xbd753c95,0xbc163d7d,0x3d553d0e,0x3d5cbd04,0xbbc9bd7f,0xbd71bcac,0x3d80,0x3d673cdb,0x3d46bd22,0xbc79bd78,0xbd7bbc48,0xbd183d4e,0x3cf13d62,0x3d80bb49,
0x3d6dbcc4,0x3b49bd80,0xbd62bcf1,0xbd4e3d18,0x3c483d7b,0x3d783c79,0x3d22bd46,0xbcdbbd67,0xbd353d35,0x3cac3d71,0x3d7f3bc9,0x3d04bd5c,0xbd0ebd55,0xbd7d3c16,0xbc953d75,0x3d3e3d2c,
0xbd7b3c48,0xbcdb3d67,0x3cf13d62,0x3d7d3c16,0x3d6d3cc4,0x3d5cbd04,0x3bc9bd7f,0xbd3ebd2c,0xbd0ebd55,0xbd80bb49,0xbd223d46,0x3c793d78,0x3d80,0x3d4e3d18,0x3d75bc95,0x3cacbd71,
0x3d553d0e,0x3d71bcac,0x3c95bd75,0xbd18bd4e,0xbcc4bd6d,0xbd78bc79,0xbd463d22,0x3b493d80,0xbc483d7b,0x3d2c3d3e,0x3d7fbbc9,0x3d04bd5c,0x3d35bd35,0xbc16bd7d,0xbd62bcf1,0xbd673cdb,
0xbd353d35,0xbb493d80,0x3d223d46,0x3d7d3c16,0x3d55bd0e,0x3c79bd78,0xbcf1bd62,0xbd71bcac,0xbd6d3cc4,0xbcdb3d67,0x3c953d75,0x3d5c3d04,0x3d7bbc48,0x3d18bd4e,0xbbc9bd7f,0xbd3ebd2c,
0x3d80,0x3d2c3d3e,0x3d7f3bc9,0x3d4ebd18,0x3c48bd7b,0xbd04bd5c,0xbd75bc95,0xbd673cdb,0xbcc43d6d,0x3cac3d71,0x3d623cf1,0x3d78bc79,0x3d0ebd55,0xbc16bd7d,0xbd46bd22,0xbd803b49,
0xbd7bbc48,0xbd713cac,0xbd223d46,0xbc163d7d,0x3d35bd35,0x3c79bd78,0xbc95bd75,0xbd3ebd2c,0x3d0ebd55,0x3b49bd80,0xbcf1bd62,0xbd5cbd04,0x3cc43d6d,0x3d4e3d18,0x3d7f3bc9,0x3d67bcdb,
0x3d55bd0e,0x3cdbbd67,0xbbc9bd7f,0xbd18bd4e,0x3d80,0x3d043d5c,0x3d623cf1,0x3d80bb49,0x3c483d7b,0x3d2c3d3e,0x3d753c95,0x3d78bc79,0xbd6dbcc4,0xbd7d3c16,0xbd463d22,0xbcac3d71,
0x3d6dbcc4,0x3d3ebd2c,0x3cf1bd62,0x3c16bd7d,0xbc48bd7b,0xbd04bd5c,0xbd46bd22,0xbd71bcac,0xbd353d35,0xbcdb3d67,0xbbc93d7f,0x3c793d78,0x3d0e3d55,0x3d4e3d18,0x3d753c95,0x3d80bb49,
0x3cc4bd6d,0x3b49bd80,0xbc95bd75,0xbd18bd4e,0xbd55bd0e,0xbd78bc79,0xbd7f3bc9,0xbd673cdb,0x3d80,0x3cac3d71,0x3d223d46,0x3d5c3d04,0x3d7b3c48,0x3d7dbc16,0x3d62bcf1,0x3d2cbd3e,
0xbd55bd0e,0xbd67bcdb,0xbd75bc95,0xbd7dbc16,0xbcc4bd6d,0xbd04bd5c,0xbd22bd46,0xbd3ebd2c,0x3c48bd7b,0x3b49bd80,0xbbc9bd7f,0xbc79bd78,0x3d35bd35,0x3d18bd4e,0x3cf1bd62,0x3cacbd71,
0x3d7bbc48,0x3d71bcac,0x3d62bcf1,0x3d4ebd18,0x3d6d3cc4,0x3d783c79,0x3d7f3bc9,0x3d80bb49,0x3d0e3d55,0x3d2c3d3e,0x3d463d22,0x3d5c3d04,0x3d80,0x3c163d7d,0x3c953d75,0x3cdb3d67,
0xbd800000,0xbb493d80,0x3d7f3bc9,0x3c16bd7d,0xbd7bbc48,0xbc793d78,0x3d753c95,0x3cacbd71,0xbd6dbcc4,0xbcdb3d67,0x3d623cf1,0x3d04bd5c,0xbd55bd0e,0xbd183d4e,0x3d463d22,0x3d2cbd3e,
0xbd35bd35,0xbd3e3d2c,0x3d223d46,0x3d4ebd18,0xbd0ebd55,0xbd5c3d04,0x3cf13d62,0x3d67bcdb,0xbcc4bd6d,0xbd713cac,0x3c953d75,0x3d78bc79,0xbc48bd7b,0xbd7d3c16,0x3bc93d7f,0x3d80bb49,
0xbd0ebd55,0xbd713cac,0x3bc93d7f,0x3d7d3c16,0xbd800000,0xbc793d78,0x3d623cf1,0x3d2cbd3e,0x3d7bbc48,0x3b49bd80,0xbd75bc95,0xbd043d5c,0x3cc4bd6d,0xbd4ebd18,0xbd463d22,0x3cdb3d67,
0xbc483d7b,0x3d673cdb,0x3d22bd46,0xbd18bd4e,0x3d353d35,0x3d5cbd04,0xbc95bd75,0xbd803b49,0xbd55bd0e,0xbd3e3d2c,0x3cf13d62,0x3d78bc79,0xbd6d3cc4,0x3c163d7d,0x3d7f3bc9,0x3cacbd71,
0x3d6d3cc4,0x3d3ebd2c,0xbc95bd75,0xbd7dbc16,0xbd0e3d55,0x3d043d5c,0x3d7fbbc9,0x3cacbd71,0xbd800000,0xbcdb3d67,0x3d223d46,0x3d78bc79,0x3c48bd7b,0xbd4ebd18,0xbd623cf1,0x3b493d80,
0x3cc43d6d,0x3d803b49,0x3cf1bd62,0xbd18bd4e,0xbd7b3c48,0xbc793d78,0x3d463d22,0x3d67bcdb,0xbd35bd35,0xbd713cac,0xbbc93d7f,0x3d5c3d04,0x3d55bd0e,0xbc16bd7d,0xbd75bc95,0xbd2c3d3e,
0xbc48bd7b,0xbd67bcdb,0xbd623cf1,0xbc163d7d,0xbcc43d6d,0x3d043d5c,0x3d7f3bc9,0x3d2cbd3e,0x3d55bd0e,0x3b49bd80,0xbd46bd22,0xbd783c79,0xbd800000,0xbd183d4e,0x3c953d75,0x3d713cac,
0xbd0e3d55,0x3cac3d71,0x3d753c95,0x3d4ebd18,0x3d6dbcc4,0x3c79bd78,0xbd22bd46,0xbd803b49,0xbd7bbc48,0xbd3e3d2c,0x3bc93d7f,0x3d5c3d04,0x3d353d35,0x3d7dbc16,0x3cf1bd62,0xbcdbbd67,
0xbd35bd35,0xbd80bb49,0xbd463d22,0xbc163d7d,0x3d0e3d55,0x3d783c79,0x3d62bcf1,0x3cacbd71,0xbcc4bd6d,0xbd67bcdb,0xbd753c95,0xbd043d5c,0x3c483d7b,0x3d4e3d18,0x3d7fbbc9,0x3d2cbd3e,
0xbd800000,0xbd3e3d2c,0xbbc93d7f,0x3d183d4e,0x3d7b3c48,0x3d5cbd04,0x3c95bd75,0xbcdbbd67,0xbd6dbcc4,0xbd713cac,0xbcf13d62,0x3c793d78,0x3d553d0e,0x3d7dbc16,0x3d22bd46,0xbb49bd80,
0x3c48bd7b,0xbcacbd71,0xbd46bd22,0xbd7dbc16,0x3d353d35,0x3d783c79,0x3d75bc95,0x3d2cbd3e,0x3d553d0e,0x3d803b49,0x3d62bcf1,0x3d04bd5c,0xbd6d3cc4,0xbd183d4e,0xbbc93d7f,0x3cdb3d67,
0x3d0e3d55,0x3d673cdb,0x3d7fbbc9,0x3d4ebd18,0xbd800000,0xbd5c3d04,0xbcf13d62,0x3b493d80,0xbd7b3c48,0xbd3e3d2c,0xbc953d75,0x3c793d78,0x3cc4bd6d,0xbc16bd7d,0xbd22bd46,0xbd71bcac,
0x3cc43d6d,0x3d2c3d3e,0x3d623cf1,0x3d7d3c16,0x3d7bbc48,0x3d5cbd04,0x3d22bd46,0x3cacbd71,0xbd35bd35,0xbd67bcdb,0xbd7fbbc9,0xbd783c79,0xbd553d0e,0xbd183d4e,0xbc953d75,0x3b493d80,
0x3d6d3cc4,0x3d803b49,0x3d75bc95,0x3d4ebd18,0x3d0ebd55,0x3c79bd78,0xbbc9bd7f,0xbcdbbd67,0xbd800000,0xbd713cac,0xbd463d22,0xbd043d5c,0xbc483d7b,0x3c163d7d,0x3cf13d62,0x3d3e3d2c,
0x3d0ebd55,0x3cdbbd67,0x3c95bd75,0x3c16bd7d,0x3d6dbcc4,0x3d5cbd04,0x3d46bd22,0x3d2cbd3e,0x3d7b3c48,0x3d803b49,0x3d7fbbc9,0x3d78bc79,0x3d353d35,0x3d4e3d18,0x3d623cf1,0x3d713cac,
0x3c483d7b,0x3cac3d71,0x3cf13d62,0x3d183d4e,0xbcc43d6d,0xbc793d78,0xbbc93d7f,0x3b493d80,0xbd553d0e,0xbd3e3d2c,0xbd223d46,0xbd043d5c,0xbd800000,0xbd7d3c16,0xbd753c95,0xbd673cdb,
0x3d80,0xbbc93d7f,0xbc483d7b,0xbc953d75,0xbcc43d6d,0xbcf13d62,0xbd0e3d55,0xbd223d46,0xbd353d35,0xbd463d22,0xbd553d0e,0xbd623cf1,0xbd6d3cc4,0xbd753c95,0xbd7b3c48,0xbd7f3bc9,
0xbd800000,0xbd7fbbc9,0xbd7bbc48,0xbd75bc95,0xbd6dbcc4,0xbd62bcf1,0xbd55bd0e,0xbd46bd22,0xbd35bd35,0xbd22bd46,0xbd0ebd55,0xbcf1bd62,0xbcc4bd6d,0xbc95bd75,0xbc48bd7b,0xbbc9bd7f,
0xbd6d3cc4,0xbd7f3bc9,0xbd7bbc48,0xbd62bcf1,0x3d80,0xbc953d75,0xbd0e3d55,0xbd463d22,0x3cc4bd6d,0x3d22bd46,0x3d55bd0e,0x3d75bc95,0xbd35bd35,0xbcf1bd62,0xbc48bd7b,0x3bc9bd7f,
0x3cc43d6d,0x3bc93d7f,0xbc483d7b,0xbcf13d62,0x3d800000,0x3d753c95,0x3d553d0e,0x3d223d46,0xbd6dbcc4,0xbd46bd22,0xbd0ebd55,0xbc95bd75,0xbd353d35,0xbd623cf1,0xbd7b3c48,0xbd7fbbc9,
0x3d35bd35,0x3d75bc95,0x3d7b3c48,0x3d463d22,0x3cc43d6d,0xbbc93d7f,0xbd0e3d55,0xbd623cf1,0x3d80,0xbcf13d62,0xbd553d0e,0xbd7f3bc9,0xbd6dbcc4,0xbd22bd46,0xbc48bd7b,0x3c95bd75,
0x3d353d35,0x3c953d75,0xbc483d7b,0xbd223d46,0xbd6d3cc4,0xbd7fbbc9,0xbd55bd0e,0xbcf1bd62,0xbd800000,0xbd62bcf1,0xbd0ebd55,0xbbc9bd7f,0x3cc4bd6d,0x3d46bd22,0x3d7bbc48,0x3d753c95,
0xbd6dbcc4,0xbcf1bd62,0x3c48bd7b,0x3d46bd22,0x3d353d35,0x3bc93d7f,0xbd0e3d55,0xbd753c95,0xbcc4bd6d,0x3c95bd75,0x3d55bd0e,0x3d7f3bc9,0x3d80,0xbd223d46,0xbd7b3c48,0xbd62bcf1,
0xbcc43d6d,0xbd623cf1,0xbd7bbc48,0xbd22bd46,0x3d35bd35,0x3d7fbbc9,0x3d553d0e,0x3c953d75,0xbd6d3cc4,0xbd75bc95,0xbd0ebd55,0x3bc9bd7f,0x3d800000,0x3d463d22,0x3c483d7b,0xbcf13d62,
0xbd800000,0xbd22bd46,0x3c48bd7b,0x3d62bcf1,0x3d6d3cc4,0x3c953d75,0xbd0e3d55,0xbd7f3bc9,0xbd35bd35,0x3bc9bd7f,0x3d55bd0e,0x3d753c95,0x3cc43d6d,0xbcf13d62,0xbd7b3c48,0xbd46bd22,
0x3d80,0xbd463d22,0xbd7bbc48,0xbcf1bd62,0x3cc4bd6d,0x3d75bc95,0x3d553d0e,0x3bc93d7f,0xbd353d35,0xbd7fbbc9,0xbd0ebd55,0x3c95bd75,0x3d6dbcc4,0x3d623cf1,0x3c483d7b,0xbd223d46,
0xbcc4bd6d,0x3d22bd46,0x3d7b3c48,0x3c953d75,0x3d800000,0x3cf13d62,0xbd0e3d55,0xbd7fbbc9,0x3d6d3cc4,0x3bc93d7f,0xbd553d0e,0xbd62bcf1,0xbd353d35,0xbd75bc95,0xbc48bd7b,0x3d46bd22,
0x3d6dbcc4,0x3d463d22,0xbc483d7b,0xbd753c95,0x3d80,0xbd623cf1,0xbd55bd0e,0x3bc9bd7f,0xbcc43d6d,0xbd7f3bc9,0xbd0ebd55,0x3cf1bd62,0xbd35bd35,0x3c95bd75,0x3d7bbc48,0x3d223d46,
0x3d353d35,0xbcf13d62,0xbd7bbc48,0xbbc9bd7f,0x3d6dbcc4,0x3d223d46,0xbd0e3d55,0xbd75bc95,0xbd800000,0xbc95bd75,0x3d55bd0e,0x3d463d22,0xbcc43d6d,0xbd7fbbc9,0xbc48bd7b,0x3d62bcf1,
0x3d35bd35,0x3d623cf1,0xbc483d7b,0xbd7f3bc9,0xbcc4bd6d,0x3d46bd22,0x3d553d0e,0xbc953d75,0x3d80,0xbd753c95,0xbd0ebd55,0x3d22bd46,0x3d6d3cc4,0xbbc93d7f,0xbd7b3c48,0xbcf1bd62,
0x3cc4bd6d,0x3d753c95,0xbc483d7b,0xbd7fbbc9,0x3d35bd35,0x3d463d22,0xbd0e3d55,0xbd62bcf1,0x3d6dbcc4,0x3cf13d62,0xbd553d0e,0xbd22bd46,0x3d800000,0x3bc93d7f,0xbd7b3c48,0xbc95bd75,
0x3d6d3cc4,0xbc953d75,0xbd7bbc48,0x3bc9bd7f,0x3d353d35,0xbd223d46,0xbd55bd0e,0x3cf1bd62,0x3cc43d6d,0xbd623cf1,0xbd0ebd55,0x3d46bd22,0x3d80,0xbd7f3bc9,0xbc48bd7b,0x3d75bc95,
0xbd800000,0xbd7fbbc9,0xbd7bbc48,0xbd75bc95,0xbd6dbcc4,0xbd62bcf1,0xbd55bd0e,0xbd46bd22,0xbd35bd35,0xbd22bd46,0xbd0ebd55,0xbcf1bd62,0xbcc4bd6d,0xbc95bd75,0xbc48bd7b,0xbbc9bd7f,
0x8000bd80,0x3bc9bd7f,0x3c48bd7b,0x3c95bd75,0x3cc4bd6d,0x3cf1bd62,0x3d0ebd55,0x3d22bd46,0x3d35bd35,0x3d46bd22,0x3d55bd0e,0x3d62bcf1,0x3d6dbcc4,0x3d75bc95,0x3d7bbc48,0x3d7fbbc9,
0xbcc4bd6d,0xbbc9bd7f,0x3c48bd7b,0x3cf1bd62,0xbd800000,0xbd75bc95,0xbd55bd0e,0xbd22bd46,0x3d6d3cc4,0x3d463d22,0x3d0e3d55,0x3c953d75,0x3d35bd35,0x3d62bcf1,0x3d7bbc48,0x3d7f3bc9,
0xbd6d3cc4,0xbd7f3bc9,0xbd7bbc48,0xbd62bcf1,0x80003d80,0xbc953d75,0xbd0e3d55,0xbd463d22,0x3cc4bd6d,0x3d22bd46,0x3d55bd0e,0x3d75bc95,0xbd35bd35,0xbcf1bd62,0xbc48bd7b,0x3bc9bd7f,
0x3d353d35,0x3c953d75,0xbc483d7b,0xbd223d46,0xbd6d3cc4,0xbd7fbbc9,0xbd55bd0e,0xbcf1bd62,0xbd800000,0xbd62bcf1,0xbd0ebd55,0xbbc9bd7f,0x3cc4bd6d,0x3d46bd22,0x3d7bbc48,0x3d753c95,
0xbd353d35,0xbd753c95,0xbd7bbc48,0xbd46bd22,0xbcc4bd6d,0x3bc9bd7f,0x3d0ebd55,0x3d62bcf1,0x8000bd80,0x3cf1bd62,0x3d55bd0e,0x3d7fbbc9,0x3d6d3cc4,0x3d223d46,0x3c483d7b,0xbc953d75,
0x3cc4bd6d,0x3d62bcf1,0x3d7b3c48,0x3d223d46,0xbd353d35,0xbd7f3bc9,0xbd55bd0e,0xbc95bd75,0x3d6dbcc4,0x3d753c95,0x3d0e3d55,0xbbc93d7f,0xbd800000,0xbd46bd22,0xbc48bd7b,0x3cf1bd62,
0xbd6dbcc4,0xbcf1bd62,0x3c48bd7b,0x3d46bd22,0x3d353d35,0x3bc93d7f,0xbd0e3d55,0xbd753c95,0xbcc4bd6d,0x3c95bd75,0x3d55bd0e,0x3d7f3bc9,0x80003d80,0xbd223d46,0xbd7b3c48,0xbd62bcf1,
0x8000bd80,0x3d46bd22,0x3d7b3c48,0x3cf13d62,0xbcc43d6d,0xbd753c95,0xbd55bd0e,0xbbc9bd7f,0x3d35bd35,0x3d7f3bc9,0x3d0e3d55,0xbc953d75,0xbd6d3cc4,0xbd62bcf1,0xbc48bd7b,0x3d22bd46,
0xbd800000,0xbd22bd46,0x3c48bd7b,0x3d62bcf1,0x3d6d3cc4,0x3c953d75,0xbd0e3d55,0xbd7f3bc9,0xbd35bd35,0x3bc9bd7f,0x3d55bd0e,0x3d753c95,0x3cc43d6d,0xbcf13d62,0xbd7b3c48,0xbd46bd22,
0x3d6dbcc4,0x3d463d22,0xbc483d7b,0xbd753c95,0x80003d80,0xbd623cf1,0xbd55bd0e,0x3bc9bd7f,0xbcc43d6d,0xbd7f3bc9,0xbd0ebd55,0x3cf1bd62,0xbd35bd35,0x3c95bd75,0x3d7bbc48,0x3d223d46,
0x3cc43d6d,0xbd223d46,0xbd7bbc48,0xbc95bd75,0xbd800000,0xbcf1bd62,0x3d0ebd55,0x3d7f3bc9,0xbd6dbcc4,0xbbc9bd7f,0x3d55bd0e,0x3d623cf1,0x3d35bd35,0x3d753c95,0x3c483d7b,0xbd463d22,
0xbd353d35,0xbd62bcf1,0x3c48bd7b,0x3d7fbbc9,0x3cc43d6d,0xbd463d22,0xbd55bd0e,0x3c95bd75,0x8000bd80,0x3d75bc95,0x3d0e3d55,0xbd223d46,0xbd6dbcc4,0x3bc9bd7f,0x3d7bbc48,0x3cf13d62,
0x3d353d35,0xbcf13d62,0xbd7bbc48,0xbbc9bd7f,0x3d6dbcc4,0x3d223d46,0xbd0e3d55,0xbd75bc95,0xbd800000,0xbc95bd75,0x3d55bd0e,0x3d463d22,0xbcc43d6d,0xbd7fbbc9,0xbc48bd7b,0x3d62bcf1,
0x3d6d3cc4,0xbc953d75,0xbd7bbc48,0x3bc9bd7f,0x3d353d35,0xbd223d46,0xbd55bd0e,0x3cf1bd62,0x3cc43d6d,0xbd623cf1,0xbd0ebd55,0x3d46bd22,0x80003d80,0xbd7f3bc9,0xbc48bd7b,0x3d75bc95,
0xbcc43d6d,0xbd75bc95,0x3c48bd7b,0x3d7f3bc9,0xbd353d35,0xbd46bd22,0x3d0ebd55,0x3d623cf1,0xbd6d3cc4,0xbcf1bd62,0x3d55bd0e,0x3d223d46,0xbd800000,0xbbc9bd7f,0x3d7bbc48,0x3c953d75,
0x3d80,0xbd7fbbc9,0x3c48bd7b,0x3d753c95,0xbcc43d6d,0xbd62bcf1,0x3d0ebd55,0x3d463d22,0xbd353d35,0xbd22bd46,0x3d55bd0e,0x3cf13d62,0xbd6d3cc4,0xbc95bd75,0x3d7bbc48,0x3bc93d7f,
0xbd800000,0x3bc9bd7f,0x3d7b3c48,0xbc953d75,0xbd6dbcc4,0x3cf1bd62,0x3d553d0e,0xbd223d46,0xbd35bd35,0x3d46bd22,0x3d0e3d55,0xbd623cf1,0xbcc4bd6d,0x3d75bc95,0x3c483d7b,0xbd7f3bc9,
0xbd6d3cc4,0xbbc9bd7f,0x3d7b3c48,0xbcf13d62,0x3d80,0xbd75bc95,0x3d0ebd55,0x3d223d46,0x3cc4bd6d,0x3d463d22,0xbd553d0e,0xbc95bd75,0xbd35bd35,0x3d62bcf1,0x3c483d7b,0xbd7fbbc9,
0x3cc43d6d,0xbd7f3bc9,0x3c48bd7b,0x3d623cf1,0x3d800000,0xbc953d75,0xbd55bd0e,0x3d46bd22,0xbd6dbcc4,0x3d22bd46,0x3d0e3d55,0xbd753c95,0xbd353d35,0xbcf1bd62,0x3d7bbc48,0xbbc93d7f,
0x3d35bd35,0x3c953d75,0xbd7bbc48,0x3d22bd46,0x3cc43d6d,0xbd7fbbc9,0x3d0ebd55,0x3cf13d62,0x3d80,0xbd62bcf1,0x3d55bd0e,0x3bc93d7f,0xbd6dbcc4,0x3d46bd22,0x3c483d7b,0xbd75bc95,
0x3d353d35,0xbd753c95,0x3c48bd7b,0x3d463d22,0xbd6d3cc4,0x3bc9bd7f,0x3d553d0e,0xbd623cf1,0xbd800000,0x3cf1bd62,0x3d0e3d55,0xbd7f3bc9,0x3cc4bd6d,0x3d223d46,0xbd7b3c48,0x3c95bd75,
0xbd6dbcc4,0x3d62bcf1,0xbc483d7b,0xbd22bd46,0x3d353d35,0xbd7f3bc9,0x3d0ebd55,0x3c953d75,0xbcc4bd6d,0x3d753c95,0xbd553d0e,0x3bc9bd7f,0x3d80,0xbd46bd22,0x3d7bbc48,0xbcf13d62,
0xbcc43d6d,0xbcf1bd62,0x3d7b3c48,0xbd463d22,0x3d35bd35,0x3bc93d7f,0xbd55bd0e,0x3d75bc95,0xbd6d3cc4,0x3c95bd75,0x3d0e3d55,0xbd7fbbc9,0x3d800000,0xbd223d46,0xbc48bd7b,0x3d623cf1,
0xbd800000,0x3d46bd22,0xbc483d7b,0xbcf1bd62,0x3d6d3cc4,0xbd753c95,0x3d0ebd55,0x3bc93d7f,0xbd35bd35,0x3d7f3bc9,0xbd553d0e,0x3c95bd75,0x3cc43d6d,0xbd62bcf1,0x3d7bbc48,0xbd223d46,
0x3d80,0xbd22bd46,0x3d7b3c48,0xbd623cf1,0x3cc4bd6d,0x3c953d75,0xbd55bd0e,0x3d7fbbc9,0xbd353d35,0x3bc9bd7f,0x3d0e3d55,0xbd75bc95,0x3d6dbcc4,0xbcf13d62,0xbc48bd7b,0x3d463d22,
0xbcc4bd6d,0x3d463d22,0xbd7bbc48,0x3d75bc95,0x3d800000,0xbd623cf1,0x3d0ebd55,0xbbc93d7f,0x3d6d3cc4,0xbd7f3bc9,0x3d55bd0e,0xbcf13d62,0xbd353d35,0x3c95bd75,0x3c483d7b,0xbd22bd46,
0x3d6dbcc4,0xbd223d46,0x3c48bd7b,0x3c953d75,0x3d80,0xbcf1bd62,0x3d553d0e,0xbd7fbbc9,0xbcc43d6d,0xbbc9bd7f,0x3d0e3d55,0xbd62bcf1,0xbd35bd35,0x3d753c95,0xbd7b3c48,0x3d46bd22,
0x3d353d35,0xbd62bcf1,0x3d7b3c48,0xbd7f3bc9,0x3d6dbcc4,0xbd463d22,0x3d0ebd55,0xbc953d75,0xbd800000,0x3d75bc95,0xbd553d0e,0x3d22bd46,0xbcc43d6d,0x3bc9bd7f,0x3c483d7b,0xbcf1bd62,
0x3d35bd35,0xbcf13d62,0x3c48bd7b,0x3bc93d7f,0xbcc4bd6d,0x3d223d46,0xbd55bd0e,0x3d753c95,0x3d80,0xbc95bd75,0x3d0e3d55,0xbd46bd22,0x3d6d3cc4,0xbd7fbbc9,0x3d7bbc48,0xbd623cf1,
0x3cc4bd6d,0xbc953d75,0x3c48bd7b,0xbbc93d7f,0x3d35bd35,0xbd223d46,0x3d0ebd55,0xbcf13d62,0x3d6dbcc4,0xbd623cf1,0x3d55bd0e,0xbd463d22,0x3d800000,0xbd7f3bc9,0x3d7bbc48,0xbd753c95,
0x3d6d3cc4,0xbd75bc95,0x3d7b3c48,0xbd7fbbc9,0x3d353d35,0xbd46bd22,0x3d553d0e,0xbd62bcf1,0x3cc43d6d,0xbcf1bd62,0x3d0e3d55,0xbd22bd46,0x3d80,0xbbc9bd7f,0x3c483d7b,0xbc95bd75,
0xbd800000,0x3bc9bd7f,0x3d7b3c48,0xbc953d75,0xbd6dbcc4,0x3cf1bd62,0x3d553d0e,0xbd223d46,0xbd35bd35,0x3d46bd22,0x3d0e3d55,0xbd623cf1,0xbcc4bd6d,0x3d75bc95,0x3c483d7b,0xbd7f3bc9,
0x8000bd80,0x3d7f3bc9,0xbc483d7b,0xbd75bc95,0x3cc4bd6d,0x3d623cf1,0xbd0e3d55,0xbd46bd22,0x3d35bd35,0x3d223d46,0xbd553d0e,0xbcf1bd62,0x3d6dbcc4,0x3c953d75,0xbd7b3c48,0xbbc9bd7f,
0xbcc4bd6d,0x3d7fbbc9,0xbc483d7b,0xbd62bcf1,0xbd800000,0x3c95bd75,0x3d553d0e,0xbd463d22,0x3d6d3cc4,0xbd223d46,0xbd0ebd55,0x3d75bc95,0x3d35bd35,0x3cf13d62,0xbd7b3c48,0x3bc9bd7f,
0xbd6d3cc4,0xbbc9bd7f,0x3d7b3c48,0xbcf13d62,0x80003d80,0xbd75bc95,0x3d0ebd55,0x3d223d46,0x3cc4bd6d,0x3d463d22,0xbd553d0e,0xbc95bd75,0xbd35bd35,0x3d62bcf1,0x3c483d7b,0xbd7fbbc9,
0x3d353d35,0xbd753c95,0x3c48bd7b,0x3d463d22,0xbd6d3cc4,0x3bc9bd7f,0x3d553d0e,0xbd623cf1,0xbd800000,0x3cf1bd62,0x3d0e3d55,0xbd7f3bc9,0x3cc4bd6d,0x3d223d46,0xbd7b3c48,0x3c95bd75,
0xbd353d35,0xbc95bd75,0x3d7b3c48,0xbd223d46,0xbcc4bd6d,0x3d7f3bc9,0xbd0e3d55,0xbcf1bd62,0x8000bd80,0x3d623cf1,0xbd553d0e,0xbbc9bd7f,0x3d6d3cc4,0xbd463d22,0xbc48bd7b,0x3d753c95,
0x3cc4bd6d,0x3cf13d62,0xbd7bbc48,0x3d46bd22,0xbd353d35,0xbbc9bd7f,0x3d553d0e,0xbd753c95,0x3d6dbcc4,0xbc953d75,0xbd0ebd55,0x3d7f3bc9,0xbd800000,0x3d22bd46,0x3c483d7b,0xbd62bcf1,
0xbd6dbcc4,0x3d62bcf1,0xbc483d7b,0xbd22bd46,0x3d353d35,0xbd7f3bc9,0x3d0ebd55,0x3c953d75,0xbcc4bd6d,0x3d753c95,0xbd553d0e,0x3bc9bd7f,0x80003d80,0xbd46bd22,0x3d7bbc48,0xbcf13d62,
0x8000bd80,0x3d223d46,0xbd7bbc48,0x3d62bcf1,0xbcc43d6d,0xbc95bd75,0x3d553d0e,0xbd7f3bc9,0x3d35bd35,0xbbc93d7f,0xbd0ebd55,0x3d753c95,0xbd6d3cc4,0x3cf1bd62,0x3c483d7b,0xbd46bd22,
0xbd800000,0x3d46bd22,0xbc483d7b,0xbcf1bd62,0x3d6d3cc4,0xbd753c95,0x3d0ebd55,0x3bc93d7f,0xbd35bd35,0x3d7f3bc9,0xbd553d0e,0x3c95bd75,0x3cc43d6d,0xbd62bcf1,0x3d7bbc48,0xbd223d46,
0x3d6dbcc4,0xbd223d46,0x3c48bd7b,0x3c953d75,0x80003d80,0xbcf1bd62,0x3d553d0e,0xbd7fbbc9,0xbcc43d6d,0xbbc9bd7f,0x3d0e3d55,0xbd62bcf1,0xbd35bd35,0x3d753c95,0xbd7b3c48,0x3d46bd22,
0x3cc43d6d,0xbd46bd22,0x3d7b3c48,0xbd753c95,0xbd800000,0x3d62bcf1,0xbd0e3d55,0x3bc9bd7f,0xbd6dbcc4,0x3d7fbbc9,0xbd553d0e,0x3cf1bd62,0x3d35bd35,0xbc953d75,0xbc48bd7b,0x3d223d46,
0xbd353d35,0x3cf1bd62,0xbc483d7b,0xbbc9bd7f,0x3cc43d6d,0xbd22bd46,0x3d553d0e,0xbd75bc95,0x8000bd80,0x3c953d75,0xbd0ebd55,0x3d463d22,0xbd6dbcc4,0x3d7f3bc9,0xbd7b3c48,0x3d62bcf1,
0x3d353d35,0xbd62bcf1,0x3d7b3c48,0xbd7f3bc9,0x3d6dbcc4,0xbd463d22,0x3d0ebd55,0xbc953d75,0xbd800000,0x3d75bc95,0xbd553d0e,0x3d22bd46,0xbcc43d6d,0x3bc9bd7f,0x3c483d7b,0xbcf1bd62,
0x3d6d3cc4,0xbd75bc95,0x3d7b3c48,0xbd7fbbc9,0x3d353d35,0xbd46bd22,0x3d553d0e,0xbd62bcf1,0x3cc43d6d,0xbcf1bd62,0x3d0e3d55,0xbd22bd46,0x80003d80,0xbbc9bd7f,0x3c483d7b,0xbc95bd75,
0xbcc43d6d,0x3c95bd75,0xbc483d7b,0x3bc9bd7f,0xbd353d35,0x3d22bd46,0xbd0e3d55,0x3cf1bd62,0xbd6d3cc4,0x3d62bcf1,0xbd553d0e,0x3d46bd22,0xbd800000,0x3d7fbbc9,0xbd7b3c48,0x3d75bc95,
0x3d80,0x3bc9bd7f,0xbc483d7b,0x3c95bd75,0xbcc43d6d,0x3cf1bd62,0xbd0e3d55,0x3d22bd46,0xbd353d35,0x3d46bd22,0xbd553d0e,0x3d62bcf1,0xbd6d3cc4,0x3d75bc95,0xbd7b3c48,0x3d7fbbc9,
0xbd800000,0x3d7f3bc9,0xbd7bbc48,0x3d753c95,0xbd6dbcc4,0x3d623cf1,0xbd55bd0e,0x3d463d22,0xbd35bd35,0x3d223d46,0xbd0ebd55,0x3cf13d62,0xbcc4bd6d,0x3c953d75,0xbc48bd7b,0x3bc93d7f,
0xbd6d3cc4,0x3d7fbbc9,0xbd7bbc48,0x3d623cf1,0x3d80,0x3c95bd75,0xbd0e3d55,0x3d46bd22,0x3cc4bd6d,0xbd223d46,0x3d55bd0e,0xbd753c95,0xbd35bd35,0x3cf13d62,0xbc48bd7b,0xbbc93d7f,
0x3cc43d6d,0xbbc9bd7f,0xbc483d7b,0x3cf1bd62,0x3d800000,0xbd75bc95,0x3d553d0e,0xbd22bd46,0xbd6dbcc4,0x3d463d22,0xbd0ebd55,0x3c953d75,0xbd353d35,0x3d62bcf1,0xbd7b3c48,0x3d7f3bc9,
0x3d35bd35,0xbd753c95,0x3d7b3c48,0xbd46bd22,0x3cc43d6d,0x3bc9bd7f,0xbd0e3d55,0x3d62bcf1,0x3d80,0x3cf1bd62,0xbd553d0e,0x3d7fbbc9,0xbd6dbcc4,0x3d223d46,0xbc48bd7b,0xbc953d75,
0x3d353d35,0xbc95bd75,0xbc483d7b,0x3d22bd46,0xbd6d3cc4,0x3d7f3bc9,0xbd55bd0e,0x3cf13d62,0xbd800000,0x3d623cf1,0xbd0ebd55,0x3bc93d7f,0x3cc4bd6d,0xbd463d22,0x3d7bbc48,0xbd75bc95,
0xbd6dbcc4,0x3cf13d62,0x3c48bd7b,0xbd463d22,0x3d353d35,0xbbc9bd7f,0xbd0e3d55,0x3d75bc95,0xbcc4bd6d,0xbc953d75,0x3d55bd0e,0xbd7fbbc9,0x3d80,0x3d22bd46,0xbd7b3c48,0x3d623cf1,
0xbcc43d6d,0x3d62bcf1,0xbd7bbc48,0x3d223d46,0x3d35bd35,0xbd7f3bc9,0x3d553d0e,0xbc95bd75,0xbd6d3cc4,0x3d753c95,0xbd0ebd55,0xbbc93d7f,0x3d800000,0xbd46bd22,0x3c483d7b,0x3cf1bd62,
0xbd800000,0x3d223d46,0x3c48bd7b,0xbd623cf1,0x3d6d3cc4,0xbc95bd75,0xbd0e3d55,0x3d7fbbc9,0xbd35bd35,0xbbc93d7f,0x3d55bd0e,0xbd75bc95,0x3cc43d6d,0x3cf1bd62,0xbd7b3c48,0x3d463d22,
0x3d80,0x3d46bd22,0xbd7bbc48,0x3cf13d62,0x3cc4bd6d,0xbd753c95,0x3d553d0e,0xbbc9bd7f,0xbd353d35,0x3d7f3bc9,0xbd0ebd55,0xbc953d75,0x3d6dbcc4,0xbd62bcf1,0x3c483d7b,0x3d22bd46,
0xbcc4bd6d,0xbd223d46,0x3d7b3c48,0xbc95bd75,0x3d800000,0xbcf1bd62,0xbd0e3d55,0x3d7f3bc9,0x3d6d3cc4,0xbbc9bd7f,0xbd553d0e,0x3d623cf1,0xbd353d35,0x3d753c95,0xbc48bd7b,0xbd463d22,
0x3d6dbcc4,0xbd46bd22,0xbc483d7b,0x3d75bc95,0x3d80,0x3d62bcf1,0xbd55bd0e,0xbbc93d7f,0xbcc43d6d,0x3d7fbbc9,0xbd0ebd55,0xbcf13d62,0xbd35bd35,0xbc953d75,0x3d7bbc48,0xbd22bd46,
0x3d353d35,0x3cf1bd62,0xbd7bbc48,0x3bc93d7f,0x3d6dbcc4,0xbd22bd46,0xbd0e3d55,0x3d753c95,0xbd800000,0x3c953d75,0x3d55bd0e,0xbd46bd22,0xbcc43d6d,0x3d7f3bc9,0xbc48bd7b,0xbd623cf1,
0x3d35bd35,0xbd62bcf1,0xbc483d7b,0x3d7fbbc9,0xbcc4bd6d,0xbd463d22,0x3d553d0e,0x3c95bd75,0x3d80,0x3d75bc95,0xbd0ebd55,0xbd223d46,0x3d6d3cc4,0x3bc9bd7f,0xbd7b3c48,0x3cf13d62,
0x3cc4bd6d,0xbd75bc95,0xbc483d7b,0x3d7f3bc9,0x3d35bd35,0xbd46bd22,0xbd0e3d55,0x3d623cf1,0x3d6dbcc4,0xbcf1bd62,0xbd553d0e,0x3d223d46,0x3d800000,0xbbc9bd7f,0xbd7b3c48,0x3c953d75,
0x3d6d3cc4,0x3c95bd75,0xbd7bbc48,0xbbc93d7f,0x3d353d35,0x3d22bd46,0xbd55bd0e,0xbcf13d62,0x3cc43d6d,0x3d62bcf1,0xbd0ebd55,0xbd463d22,0x3d80,0x3d7fbbc9,0xbc48bd7b,0xbd753c95,
0xbd800000,0x3d7f3bc9,0xbd7bbc48,0x3d753c95,0xbd6dbcc4,0x3d623cf1,0xbd55bd0e,0x3d463d22,0xbd35bd35,0x3d223d46,0xbd0ebd55,0x3cf13d62,0xbcc4bd6d,0x3c953d75,0xbc48bd7b,0x3bc93d7f,
0x8000bd80,0xbbc93d7f,0x3c48bd7b,0xbc953d75,0x3cc4bd6d,0xbcf13d62,0x3d0ebd55,0xbd223d46,0x3d35bd35,0xbd463d22,0x3d55bd0e,0xbd623cf1,0x3d6dbcc4,0xbd753c95,0x3d7bbc48,0xbd7f3bc9,
0xbcc4bd6d,0x3bc93d7f,0x3c48bd7b,0xbcf13d62,0xbd800000,0x3d753c95,0xbd55bd0e,0x3d223d46,0x3d6d3cc4,0xbd46bd22,0x3d0e3d55,0xbc95bd75,0x3d35bd35,0xbd623cf1,0x3d7bbc48,0xbd7fbbc9,
0xbd6d3cc4,0x3d7fbbc9,0xbd7bbc48,0x3d623cf1,0x80003d80,0x3c95bd75,0xbd0e3d55,0x3d46bd22,0x3cc4bd6d,0xbd223d46,0x3d55bd0e,0xbd753c95,0xbd35bd35,0x3cf13d62,0xbc48bd7b,0xbbc93d7f,
0x3d353d35,0xbc95bd75,0xbc483d7b,0x3d22bd46,0xbd6d3cc4,0x3d7f3bc9,0xbd55bd0e,0x3cf13d62,0xbd800000,0x3d623cf1,0xbd0ebd55,0x3bc93d7f,0x3cc4bd6d,0xbd463d22,0x3d7bbc48,0xbd75bc95,
0xbd353d35,0x3d75bc95,0xbd7bbc48,0x3d463d22,0xbcc4bd6d,0xbbc93d7f,0x3d0ebd55,0xbd623cf1,0x8000bd80,0xbcf13d62,0x3d55bd0e,0xbd7f3bc9,0x3d6d3cc4,0xbd22bd46,0x3c483d7b,0x3c95bd75,
0x3cc4bd6d,0xbd623cf1,0x3d7b3c48,0xbd22bd46,0xbd353d35,0x3d7fbbc9,0xbd55bd0e,0x3c953d75,0x3d6dbcc4,0xbd75bc95,0x3d0e3d55,0x3bc9bd7f,0xbd800000,0x3d463d22,0xbc48bd7b,0xbcf13d62,
0xbd6dbcc4,0x3cf13d62,0x3c48bd7b,0xbd463d22,0x3d353d35,0xbbc9bd7f,0xbd0e3d55,0x3d75bc95,0xbcc4bd6d,0xbc953d75,0x3d55bd0e,0xbd7fbbc9,0x80003d80,0x3d22bd46,0xbd7b3c48,0x3d623cf1,
0x8000bd80,0xbd463d22,0x3d7b3c48,0xbcf1bd62,0xbcc43d6d,0x3d75bc95,0xbd55bd0e,0x3bc93d7f,0x3d35bd35,0xbd7fbbc9,0x3d0e3d55,0x3c95bd75,0xbd6d3cc4,0x3d623cf1,0xbc48bd7b,0xbd223d46,
0xbd800000,0x3d223d46,0x3c48bd7b,0xbd623cf1,0x3d6d3cc4,0xbc95bd75,0xbd0e3d55,0x3d7fbbc9,0xbd35bd35,0xbbc93d7f,0x3d55bd0e,0xbd75bc95,0x3cc43d6d,0x3cf1bd62,0xbd7b3c48,0x3d463d22,
0x3d6dbcc4,0xbd46bd22,0xbc483d7b,0x3d75bc95,0x80003d80,0x3d62bcf1,0xbd55bd0e,0xbbc93d7f,0xbcc43d6d,0x3d7fbbc9,0xbd0ebd55,0xbcf13d62,0xbd35bd35,0xbc953d75,0x3d7bbc48,0xbd22bd46,
0x3cc43d6d,0x3d22bd46,0xbd7bbc48,0x3c953d75,0xbd800000,0x3cf13d62,0x3d0ebd55,0xbd7fbbc9,0xbd6dbcc4,0x3bc93d7f,0x3d55bd0e,0xbd62bcf1,0x3d35bd35,0xbd75bc95,0x3c483d7b,0x3d46bd22,
0xbd353d35,0x3d623cf1,0x3c48bd7b,0xbd7f3bc9,0x3cc43d6d,0x3d46bd22,0xbd55bd0e,0xbc953d75,0x8000bd80,0xbd753c95,0x3d0e3d55,0x3d22bd46,0xbd6dbcc4,0xbbc93d7f,0x3d7bbc48,0xbcf1bd62,
0x3d353d35,0x3cf1bd62,0xbd7bbc48,0x3bc93d7f,0x3d6dbcc4,0xbd22bd46,0xbd0e3d55,0x3d753c95,0xbd800000,0x3c953d75,0x3d55bd0e,0xbd46bd22,0xbcc43d6d,0x3d7f3bc9,0xbc48bd7b,0xbd623cf1,
0x3d6d3cc4,0x3c95bd75,0xbd7bbc48,0xbbc93d7f,0x3d353d35,0x3d22bd46,0xbd55bd0e,0xbcf13d62,0x3cc43d6d,0x3d62bcf1,0xbd0ebd55,0xbd463d22,0x80003d80,0x3d7fbbc9,0xbc48bd7b,0xbd753c95,
0xbcc43d6d,0x3d753c95,0x3c48bd7b,0xbd7fbbc9,0xbd353d35,0x3d463d22,0x3d0ebd55,0xbd62bcf1,0xbd6d3cc4,0x3cf13d62,0x3d55bd0e,0xbd22bd46,0xbd800000,0x3bc93d7f,0x3d7bbc48,0xbc95bd75,
0x3d80,0x3d7f3bc9,0x3c48bd7b,0xbd75bc95,0xbcc43d6d,0x3d623cf1,0x3d0ebd55,0xbd46bd22,0xbd353d35,0x3d223d46,0x3d55bd0e,0xbcf1bd62,0xbd6d3cc4,0x3c953d75,0x3d7bbc48,0xbbc9bd7f,
0xbd800000,0xbbc93d7f,0x3d7b3c48,0x3c95bd75,0xbd6dbcc4,0xbcf13d62,0x3d553d0e,0x3d22bd46,0xbd35bd35,0xbd463d22,0x3d0e3d55,0x3d62bcf1,0xbcc4bd6d,0xbd753c95,0x3c483d7b,0x3d7fbbc9,
0xbd6d3cc4,0x3bc93d7f,0x3d7b3c48,0x3cf1bd62,0x3d80,0x3d753c95,0x3d0ebd55,0xbd22bd46,0x3cc4bd6d,0xbd46bd22,0xbd553d0e,0x3c953d75,0xbd35bd35,0xbd623cf1,0x3c483d7b,0x3d7f3bc9,
0x3cc43d6d,0x3d7fbbc9,0x3c48bd7b,0xbd62bcf1,0x3d800000,0x3c95bd75,0xbd55bd0e,0xbd463d22,0xbd6dbcc4,0xbd223d46,0x3d0e3d55,0x3d75bc95,0xbd353d35,0x3cf13d62,0x3d7bbc48,0x3bc9bd7f,
0x3d35bd35,0xbc95bd75,0xbd7bbc48,0xbd223d46,0x3cc43d6d,0x3d7f3bc9,0x3d0ebd55,0xbcf1bd62,0x3d80,0x3d623cf1,0x3d55bd0e,0xbbc9bd7f,0xbd6dbcc4,0xbd463d22,0x3c483d7b,0x3d753c95,
0x3d353d35,0x3d75bc95,0x3c48bd7b,0xbd46bd22,0xbd6d3cc4,0xbbc93d7f,0x3d553d0e,0x3d62bcf1,0xbd800000,0xbcf13d62,0x3d0e3d55,0x3d7fbbc9,0x3cc4bd6d,0xbd22bd46,0xbd7b3c48,0xbc953d75,
0xbd6dbcc4,0xbd623cf1,0xbc483d7b,0x3d223d46,0x3d353d35,0x3d7fbbc9,0x3d0ebd55,0xbc95bd75,0xbcc4bd6d,0xbd75bc95,0xbd553d0e,0xbbc93d7f,0x3d80,0x3d463d22,0x3d7bbc48,0x3cf1bd62,
0xbcc43d6d,0x3cf13d62,0x3d7b3c48,0x3d46bd22,0x3d35bd35,0xbbc9bd7f,0xbd55bd0e,0xbd753c95,0xbd6d3cc4,0xbc953d75,0x3d0e3d55,0x3d7f3bc9,0x3d800000,0x3d22bd46,0xbc48bd7b,0xbd62bcf1,
0xbd800000,0xbd463d22,0xbc483d7b,0x3cf13d62,0x3d6d3cc4,0x3d75bc95,0x3d0ebd55,0xbbc9bd7f,0xbd35bd35,0xbd7fbbc9,0xbd553d0e,0xbc953d75,0x3cc43d6d,0x3d623cf1,0x3d7bbc48,0x3d22bd46,
0x3d80,0x3d223d46,0x3d7b3c48,0x3d62bcf1,0x3cc4bd6d,0xbc95bd75,0xbd55bd0e,0xbd7f3bc9,0xbd353d35,0xbbc93d7f,0x3d0e3d55,0x3d753c95,0x3d6dbcc4,0x3cf1bd62,0xbc48bd7b,0xbd46bd22,
0xbcc4bd6d,0xbd46bd22,0xbd7bbc48,0xbd753c95,0x3d800000,0x3d62bcf1,0x3d0ebd55,0x3bc9bd7f,0x3d6d3cc4,0x3d7fbbc9,0x3d55bd0e,0x3cf1bd62,0xbd353d35,0xbc953d75,0x3c483d7b,0x3d223d46,
0x3d6dbcc4,0x3d22bd46,0x3c48bd7b,0xbc95bd75,0x3d80,0x3cf13d62,0x3d553d0e,0x3d7f3bc9,0xbcc43d6d,0x3bc93d7f,0x3d0e3d55,0x3d623cf1,0xbd35bd35,0xbd75bc95,0xbd7b3c48,0xbd463d22,
0x3d353d35,0x3d623cf1,0x3d7b3c48,0x3d7fbbc9,0x3d6dbcc4,0x3d46bd22,0x3d0ebd55,0x3c95bd75,0xbd800000,0xbd753c95,0xbd553d0e,0xbd223d46,0xbcc43d6d,0xbbc93d7f,0x3c483d7b,0x3cf13d62,
0x3d35bd35,0x3cf1bd62,0x3c48bd7b,0xbbc9bd7f,0xbcc4bd6d,0xbd22bd46,0xbd55bd0e,0xbd75bc95,0x3d80,0x3c953d75,0x3d0e3d55,0x3d463d22,0x3d6d3cc4,0x3d7f3bc9,0x3d7bbc48,0x3d62bcf1,
0x3cc4bd6d,0x3c95bd75,0x3c48bd7b,0x3bc9bd7f,0x3d35bd35,0x3d22bd46,0x3d0ebd55,0x3cf1bd62,0x3d6dbcc4,0x3d62bcf1,0x3d55bd0e,0x3d46bd22,0x3d800000,0x3d7fbbc9,0x3d7bbc48,0x3d75bc95,
0x3d6d3cc4,0x3d753c95,0x3d7b3c48,0x3d7f3bc9,0x3d353d35,0x3d463d22,0x3d553d0e,0x3d623cf1,0x3cc43d6d,0x3cf13d62,0x3d0e3d55,0x3d223d46,0x3d80,0x3bc93d7f,0x3c483d7b,0x3c953d75,
0xbd800000,0xbbc93d7f,0x3d7b3c48,0x3c95bd75,0xbd6dbcc4,0xbcf13d62,0x3d553d0e,0x3d22bd46,0xbd35bd35,0xbd463d22,0x3d0e3d55,0x3d62bcf1,0xbcc4bd6d,0xbd753c95,0x3c483d7b,0x3d7fbbc9,
0x8000bd80,0xbd7fbbc9,0xbc483d7b,0x3d753c95,0x3cc4bd6d,0xbd62bcf1,0xbd0e3d55,0x3d463d22,0x3d35bd35,0xbd22bd46,0xbd553d0e,0x3cf13d62,0x3d6dbcc4,0xbc95bd75,0xbd7b3c48,0x3bc93d7f,
0xbcc4bd6d,0xbd7f3bc9,0xbc483d7b,0x3d623cf1,0xbd800000,0xbc953d75,0x3d553d0e,0x3d46bd22,0x3d6d3cc4,0x3d22bd46,0xbd0ebd55,0xbd753c95,0x3d35bd35,0xbcf1bd62,0xbd7b3c48,0xbbc93d7f,
0xbd6d3cc4,0x3bc93d7f,0x3d7b3c48,0x3cf1bd62,0x80003d80,0x3d753c95,0x3d0ebd55,0xbd22bd46,0x3cc4bd6d,0xbd46bd22,0xbd553d0e,0x3c953d75,0xbd35bd35,0xbd623cf1,0x3c483d7b,0x3d7f3bc9,
0x3d353d35,0x3d75bc95,0x3c48bd7b,0xbd46bd22,0xbd6d3cc4,0xbbc93d7f,0x3d553d0e,0x3d62bcf1,0xbd800000,0xbcf13d62,0x3d0e3d55,0x3d7fbbc9,0x3cc4bd6d,0xbd22bd46,0xbd7b3c48,0xbc953d75,
0xbd353d35,0x3c953d75,0x3d7b3c48,0x3d22bd46,0xbcc4bd6d,0xbd7fbbc9,0xbd0e3d55,0x3cf13d62,0x8000bd80,0xbd62bcf1,0xbd553d0e,0x3bc93d7f,0x3d6d3cc4,0x3d46bd22,0xbc48bd7b,0xbd75bc95,
0x3cc4bd6d,0xbcf1bd62,0xbd7bbc48,0xbd463d22,0xbd353d35,0x3bc93d7f,0x3d553d0e,0x3d75bc95,0x3d6dbcc4,0x3c95bd75,0xbd0ebd55,0xbd7fbbc9,0xbd800000,0xbd223d46,0x3c483d7b,0x3d623cf1,
0xbd6dbcc4,0xbd623cf1,0xbc483d7b,0x3d223d46,0x3d353d35,0x3d7fbbc9,0x3d0ebd55,0xbc95bd75,0xbcc4bd6d,0xbd75bc95,0xbd553d0e,0xbbc93d7f,0x80003d80,0x3d463d22,0x3d7bbc48,0x3cf1bd62,
0x8000bd80,0xbd22bd46,0xbd7bbc48,0xbd623cf1,0xbcc43d6d,0x3c953d75,0x3d553d0e,0x3d7fbbc9,0x3d35bd35,0x3bc9bd7f,0xbd0ebd55,0xbd75bc95,0xbd6d3cc4,0xbcf13d62,0x3c483d7b,0x3d463d22,
0xbd800000,0xbd463d22,0xbc483d7b,0x3cf13d62,0x3d6d3cc4,0x3d75bc95,0x3d0ebd55,0xbbc9bd7f,0xbd35bd35,0xbd7fbbc9,0xbd553d0e,0xbc953d75,0x3cc43d6d,0x3d623cf1,0x3d7bbc48,0x3d22bd46,
0x3d6dbcc4,0x3d22bd46,0x3c48bd7b,0xbc95bd75,0x80003d80,0x3cf13d62,0x3d553d0e,0x3d7f3bc9,0xbcc43d6d,0x3bc93d7f,0x3d0e3d55,0x3d623cf1,0xbd35bd35,0xbd75bc95,0xbd7b3c48,0xbd463d22,
0x3cc43d6d,0x3d463d22,0x3d7b3c48,0x3d75bc95,0xbd800000,0xbd623cf1,0xbd0e3d55,0xbbc93d7f,0xbd6dbcc4,0xbd7f3bc9,0xbd553d0e,0xbcf13d62,0x3d35bd35,0x3c95bd75,0xbc48bd7b,0xbd22bd46,
0xbd353d35,0xbcf13d62,0xbc483d7b,0x3bc93d7f,0x3cc43d6d,0x3d223d46,0x3d553d0e,0x3d753c95,0x8000bd80,0xbc95bd75,0xbd0ebd55,0xbd46bd22,0xbd6dbcc4,0xbd7fbbc9,0xbd7b3c48,0xbd623cf1,
0x3d353d35,0x3d623cf1,0x3d7b3c48,0x3d7fbbc9,0x3d6dbcc4,0x3d46bd22,0x3d0ebd55,0x3c95bd75,0xbd800000,0xbd753c95,0xbd553d0e,0xbd223d46,0xbcc43d6d,0xbbc93d7f,0x3c483d7b,0x3cf13d62,
0x3d6d3cc4,0x3d753c95,0x3d7b3c48,0x3d7f3bc9,0x3d353d35,0x3d463d22,0x3d553d0e,0x3d623cf1,0x3cc43d6d,0x3cf13d62,0x3d0e3d55,0x3d223d46,0x80003d80,0x3bc93d7f,0x3c483d7b,0x3c953d75,
0xbcc43d6d,0xbc953d75,0xbc483d7b,0xbbc93d7f,0xbd353d35,0xbd223d46,0xbd0e3d55,0xbcf13d62,0xbd6d3cc4,0xbd623cf1,0xbd553d0e,0xbd463d22,0xbd800000,0xbd7f3bc9,0xbd7b3c48,0xbd753c95,
0x3d80,0xbc163d7d,0xbc953d75,0xbcdb3d67,0xbd0e3d55,0xbd2c3d3e,0xbd463d22,0xbd5c3d04,0xbd6d3cc4,0xbd783c79,0xbd7f3bc9,0xbd80bb49,0xbd7bbc48,0xbd71bcac,0xbd62bcf1,0xbd4ebd18,
0xbd35bd35,0xbd18bd4e,0xbcf1bd62,0xbcacbd71,0xbc48bd7b,0xbb49bd80,0x3bc9bd7f,0x3c79bd78,0x3cc4bd6d,0x3d04bd5c,0x3d22bd46,0x3d3ebd2c,0x3d55bd0e,0x3d67bcdb,0x3d75bc95,0x3d7dbc16,
0xbd7b3c48,0xbd7dbc16,0xbd62bcf1,0xbd2cbd3e,0x3d80,0xbcac3d71,0xbd223d46,0xbd5c3d04,0x3d55bd0e,0x3d78bc79,0x3d7f3bc9,0x3d673cdb,0xbcc4bd6d,0xbb49bd80,0x3c95bd75,0x3d18bd4e,
0xbd0e3d55,0xbd4e3d18,0xbd753c95,0xbd80bb49,0x3d353d35,0x3cdb3d67,0x3bc93d7f,0xbc793d78,0x3c48bd7b,0x3d04bd5c,0x3d46bd22,0x3d71bcac,0xbd6dbcc4,0xbd3ebd2c,0xbcf1bd62,0xbc16bd7d,
0x3d6dbcc4,0x3d7d3c16,0x3d463d22,0x3cac3d71,0xbc483d7b,0xbd2c3d3e,0xbd753c95,0xbd78bc79,0x3d80,0xbd043d5c,0xbd623cf1,0xbd80bb49,0xbd55bd0e,0xbcdbbd67,0x3bc9bd7f,0x3d18bd4e,
0xbcc43d6d,0xbd4e3d18,0xbd7f3bc9,0xbd67bcdb,0xbd0ebd55,0xbb49bd80,0x3cf1bd62,0x3d5cbd04,0xbd35bd35,0xbc79bd78,0x3c95bd75,0x3d3ebd2c,0x3d7bbc48,0x3d713cac,0x3d223d46,0x3c163d7d,
0xbd0ebd55,0x3c16bd7d,0x3d46bd22,0x3d803b49,0x3cc43d6d,0xbcac3d71,0xbd623cf1,0xbd78bc79,0xbc48bd7b,0x3d04bd5c,0x3d75bc95,0x3d673cdb,0x3d80,0xbd2c3d3e,0xbd7f3bc9,0xbd4ebd18,
0xbd7bbc48,0xbd18bd4e,0x3bc9bd7f,0x3d3ebd2c,0x3d6d3cc4,0x3cdb3d67,0xbc953d75,0xbd5c3d04,0xbd55bd0e,0xbc79bd78,0x3cf1bd62,0x3d71bcac,0x3d353d35,0x3b493d80,0xbd223d46,0xbd7d3c16,
0xbd35bd35,0x3c16bd7d,0x3d62bcf1,0x3d673cdb,0x3c483d7b,0xbd2c3d3e,0xbd7fbbc9,0xbd04bd5c,0x3cc4bd6d,0x3d78bc79,0x3d463d22,0xbb493d80,0xbd553d0e,0xbd71bcac,0xbc95bd75,0x3d18bd4e,
0x3d80,0xbd4e3d18,0xbd75bc95,0xbcacbd71,0x3d0ebd55,0x3d80bb49,0x3d223d46,0xbc793d78,0xbd6d3cc4,0xbd5cbd04,0xbbc9bd7f,0x3d3ebd2c,0x3d7b3c48,0x3cdb3d67,0xbcf13d62,0xbd7d3c16,
0x3d0ebd55,0x3d7d3c16,0x3c953d75,0xbd3e3d2c,0x3d353d35,0xbcac3d71,0xbd7f3bc9,0xbd04bd5c,0xbc483d7b,0xbd783c79,0xbd22bd46,0x3cdbbd67,0xbd6dbcc4,0xbb49bd80,0x3d62bcf1,0x3d4e3d18,
0x3d7bbc48,0x3d183d4e,0xbcf13d62,0xbd80bb49,0x3d80,0xbd673cdb,0xbd46bd22,0x3c79bd78,0xbd553d0e,0xbd5cbd04,0x3bc9bd7f,0x3d71bcac,0xbcc4bd6d,0x3d2cbd3e,0x3d753c95,0x3c163d7d,
0xbcc43d6d,0xbd7dbc16,0xbbc9bd7f,0x3d71bcac,0x3d0e3d55,0xbd2c3d3e,0xbd62bcf1,0x3c79bd78,0xbd35bd35,0x3d04bd5c,0x3d753c95,0xbb493d80,0xbd7b3c48,0xbcdbbd67,0x3d46bd22,0x3d4e3d18,
0x3d6dbcc4,0x3d183d4e,0xbd223d46,0xbd67bcdb,0x3c48bd7b,0x3d80bb49,0x3c953d75,0xbd5c3d04,0x3d80,0xbd783c79,0xbcf1bd62,0x3d3ebd2c,0x3d553d0e,0xbcac3d71,0xbd7fbbc9,0xbc16bd7d,
0x3d7b3c48,0xbc163d7d,0xbd7fbbc9,0x3b49bd80,0x3d6d3cc4,0xbcac3d71,0xbd75bc95,0x3c79bd78,0x3d553d0e,0xbd043d5c,0xbd62bcf1,0x3cdbbd67,0x3d353d35,0xbd2c3d3e,0xbd46bd22,0x3d18bd4e,
0x3d0e3d55,0xbd4e3d18,0xbd22bd46,0x3d3ebd2c,0x3cc43d6d,0xbd673cdb,0xbcf1bd62,0x3d5cbd04,0x3c483d7b,0xbd783c79,0xbc95bd75,0x3d71bcac,0x3d80,0xbd803b49,0xbbc9bd7f,0x3d7dbc16,
0xbd800000,0xbd7dbc16,0xbd75bc95,0xbd67bcdb,0xbd55bd0e,0xbd3ebd2c,0xbd22bd46,0xbd04bd5c,0xbcc4bd6d,0xbc79bd78,0xbbc9bd7f,0x3b49bd80,0x3c48bd7b,0x3cacbd71,0x3cf1bd62,0x3d18bd4e,
0x3d35bd35,0x3d4ebd18,0x3d62bcf1,0x3d71bcac,0x3d7bbc48,0x3d80bb49,0x3d7f3bc9,0x3d783c79,0x3d6d3cc4,0x3d5c3d04,0x3d463d22,0x3d2c3d3e,0x3d0e3d55,0x3cdb3d67,0x3c953d75,0x3c163d7d,
0xbc48bd7b,0x3c16bd7d,0x3cf1bd62,0x3d3ebd2c,0xbd800000,0xbd71bcac,0xbd46bd22,0xbd04bd5c,0x3d0e3d55,0x3c793d78,0xbbc93d7f,0xbcdb3d67,0x3d6dbcc4,0x3d80bb49,0x3d753c95,0x3d4e3d18,
0xbd55bd0e,0xbd18bd4e,0xbc95bd75,0x3b49bd80,0xbd353d35,0xbd673cdb,0xbd7f3bc9,0xbd78bc79,0x3d7b3c48,0x3d5c3d04,0x3d223d46,0x3cac3d71,0x3cc4bd6d,0x3d2cbd3e,0x3d62bcf1,0x3d7dbc16,
0x3cc43d6d,0xbc163d7d,0xbd223d46,0xbd713cac,0xbd7bbc48,0xbd3ebd2c,0xbc95bd75,0x3c79bd78,0xbd800000,0xbd5cbd04,0xbcf1bd62,0x3b49bd80,0x3d0ebd55,0x3d67bcdb,0x3d7f3bc9,0x3d4e3d18,
0xbd6dbcc4,0xbd18bd4e,0xbbc9bd7f,0x3cdbbd67,0x3d55bd0e,0x3d80bb49,0x3d623cf1,0x3d043d5c,0x3d35bd35,0x3d78bc79,0x3d753c95,0x3d2c3d3e,0x3c483d7b,0xbcac3d71,0xbd463d22,0xbd7d3c16,
0x3d55bd0e,0x3d7d3c16,0x3d223d46,0xbb493d80,0xbd6d3cc4,0xbd71bcac,0xbcf1bd62,0x3c79bd78,0x3d7bbc48,0x3d5c3d04,0x3c953d75,0xbcdb3d67,0xbd800000,0xbd3ebd2c,0xbbc9bd7f,0x3d18bd4e,
0x3c48bd7b,0x3d4ebd18,0x3d7f3bc9,0x3d2c3d3e,0xbcc43d6d,0xbd673cdb,0xbd75bc95,0xbd04bd5c,0x3d0ebd55,0x3d78bc79,0x3d623cf1,0x3cac3d71,0xbd353d35,0xbd803b49,0xbd46bd22,0xbc16bd7d,
0x3d35bd35,0x3d7d3c16,0x3cf13d62,0xbcdb3d67,0xbd7b3c48,0xbd3ebd2c,0x3bc9bd7f,0x3d5cbd04,0x3d6d3cc4,0x3c793d78,0xbd223d46,0xbd80bb49,0xbd0ebd55,0x3cacbd71,0x3d75bc95,0x3d4e3d18,
0xbd800000,0xbd18bd4e,0x3c95bd75,0x3d71bcac,0x3d553d0e,0x3b493d80,0xbd463d22,0xbd78bc79,0xbcc4bd6d,0x3d04bd5c,0x3d7fbbc9,0x3d2c3d3e,0xbc483d7b,0xbd673cdb,0xbd62bcf1,0xbc16bd7d,
0x3d553d0e,0xbc163d7d,0xbd753c95,0xbd2cbd3e,0xbd353d35,0xbd71bcac,0xbbc9bd7f,0x3d5cbd04,0xbd7bbc48,0xbc79bd78,0x3d46bd22,0x3d673cdb,0x3cc4bd6d,0x3d80bb49,0x3cf13d62,0xbd183d4e,
0x3c483d7b,0xbd4e3d18,0xbd62bcf1,0x3b49bd80,0xbd800000,0xbcdbbd67,0x3d22bd46,0x3d783c79,0xbd0ebd55,0x3d04bd5c,0x3d7f3bc9,0x3cac3d71,0x3d6dbcc4,0x3d3e3d2c,0xbc953d75,0xbd7d3c16,
0xbd6dbcc4,0x3c16bd7d,0x3d7fbbc9,0x3cac3d71,0xbd553d0e,0xbd3ebd2c,0x3cf1bd62,0x3d783c79,0x3d35bd35,0x3d5c3d04,0xbc953d75,0xbd80bb49,0xbc48bd7b,0x3d67bcdb,0x3d223d46,0xbd183d4e,
0x3cc43d6d,0xbd4e3d18,0xbd46bd22,0x3cdbbd67,0x3d7b3c48,0x3b493d80,0xbd753c95,0xbd04bd5c,0xbd800000,0xbc79bd78,0x3d62bcf1,0x3d2c3d3e,0xbd0e3d55,0xbd71bcac,0x3bc9bd7f,0x3d7dbc16,
0xbc483d7b,0xbd7dbc16,0x3bc9bd7f,0x3d803b49,0xbcc43d6d,0xbd71bcac,0x3c95bd75,0x3d783c79,0xbd0e3d55,0xbd5cbd04,0x3cf1bd62,0x3d673cdb,0xbd353d35,0xbd3ebd2c,0x3d22bd46,0x3d4e3d18,
0xbd553d0e,0xbd18bd4e,0x3d46bd22,0x3d2c3d3e,0xbd6d3cc4,0xbcdbbd67,0x3d62bcf1,0x3d043d5c,0xbd7b3c48,0xbc79bd78,0x3d75bc95,0x3cac3d71,0xbd800000,0xbb49bd80,0x3d7fbbc9,0x3c163d7d,
0x3d80,0xbd7dbc16,0x3c95bd75,0x3d673cdb,0xbd0e3d55,0xbd3ebd2c,0x3d46bd22,0x3d043d5c,0xbd6d3cc4,0xbc79bd78,0x3d7fbbc9,0xbb493d80,0xbd7bbc48,0x3cacbd71,0x3d623cf1,0xbd183d4e,
0xbd35bd35,0x3d4ebd18,0x3cf13d62,0xbd713cac,0xbc48bd7b,0x3d80bb49,0xbbc93d7f,0xbd78bc79,0x3cc4bd6d,0x3d5c3d04,0xbd223d46,0xbd2cbd3e,0x3d55bd0e,0x3cdb3d67,0xbd753c95,0xbc16bd7d,
0xbd7b3c48,0x3c16bd7d,0x3d623cf1,0xbd3e3d2c,0x3d80,0xbd71bcac,0x3d22bd46,0x3d043d5c,0x3d55bd0e,0x3c793d78,0xbd7fbbc9,0x3cdbbd67,0xbcc4bd6d,0x3d80bb49,0xbc953d75,0xbd4ebd18,
0xbd0e3d55,0xbd18bd4e,0x3d75bc95,0xbb493d80,0x3d353d35,0xbd673cdb,0xbbc9bd7f,0x3d783c79,0x3c48bd7b,0x3d5c3d04,0xbd463d22,0xbcacbd71,0xbd6dbcc4,0x3d2cbd3e,0x3cf13d62,0xbd7d3c16,
0x3d6dbcc4,0xbc163d7d,0xbd46bd22,0x3d71bcac,0xbc483d7b,0xbd3ebd2c,0x3d75bc95,0xbc793d78,0x3d80,0xbd5cbd04,0x3d62bcf1,0xbb493d80,0xbd55bd0e,0x3d67bcdb,0xbbc93d7f,0xbd4ebd18,
0xbcc43d6d,0xbd18bd4e,0x3d7fbbc9,0xbcdb3d67,0xbd0ebd55,0x3d80bb49,0xbcf13d62,0xbd04bd5c,0xbd35bd35,0x3d78bc79,0xbc953d75,0xbd2cbd3e,0x3d7bbc48,0xbcac3d71,0xbd22bd46,0x3d7dbc16,
0xbd0ebd55,0x3d7d3c16,0xbd463d22,0x3b49bd80,0x3cc43d6d,0xbd71bcac,0x3d62bcf1,0xbc793d78,0xbc48bd7b,0x3d5c3d04,0xbd753c95,0x3cdbbd67,0x3d80,0xbd3ebd2c,0x3d7fbbc9,0xbd183d4e,
0xbd7bbc48,0x3d4ebd18,0xbbc93d7f,0xbd2cbd3e,0x3d6d3cc4,0xbd673cdb,0x3c95bd75,0x3d043d5c,0xbd55bd0e,0x3d78bc79,0xbcf13d62,0xbcacbd71,0x3d353d35,0xbd803b49,0x3d22bd46,0x3c163d7d,
0xbd35bd35,0x3d7d3c16,0xbd623cf1,0x3cdbbd67,0x3c483d7b,0xbd3ebd2c,0x3d7f3bc9,0xbd5c3d04,0x3cc4bd6d,0x3c793d78,0xbd46bd22,0x3d803b49,0xbd553d0e,0x3cacbd71,0x3c953d75,0xbd4ebd18,
0x3d80,0xbd18bd4e,0x3d753c95,0xbd713cac,0x3d0ebd55,0x3b493d80,0xbd22bd46,0x3d783c79,0xbd6d3cc4,0x3d04bd5c,0x3bc93d7f,0xbd2cbd3e,0x3d7b3c48,0xbd673cdb,0x3cf1bd62,0x3c163d7d,
0x3d0ebd55,0xbc163d7d,0xbc95bd75,0x3d2c3d3e,0x3d353d35,0xbd71bcac,0x3d7fbbc9,0xbd5c3d04,0xbc483d7b,0xbc79bd78,0x3d223d46,0xbd67bcdb,0xbd6dbcc4,0x3d80bb49,0xbd623cf1,0x3d18bd4e,
0x3d7bbc48,0xbd4e3d18,0x3cf1bd62,0xbb493d80,0x3d80,0xbcdbbd67,0x3d463d22,0xbd78bc79,0xbd553d0e,0x3d04bd5c,0xbbc93d7f,0xbcacbd71,0xbcc4bd6d,0x3d3e3d2c,0xbd75bc95,0x3d7dbc16,
0xbcc43d6d,0x3c16bd7d,0x3bc93d7f,0xbcacbd71,0x3d0e3d55,0xbd3ebd2c,0x3d623cf1,0xbd78bc79,0xbd35bd35,0x3d5c3d04,0xbd75bc95,0x3d803b49,0xbd7b3c48,0x3d67bcdb,0xbd463d22,0x3d18bd4e,
0x3d6dbcc4,0xbd4e3d18,0x3d22bd46,0xbcdb3d67,0x3c48bd7b,0x3b493d80,0xbc95bd75,0x3d043d5c,0x3d80,0xbc79bd78,0x3cf13d62,0xbd2cbd3e,0x3d553d0e,0xbd71bcac,0x3d7f3bc9,0xbd7d3c16,
0x3d7b3c48,0xbd7dbc16,0x3d7f3bc9,0xbd80bb49,0x3d6d3cc4,0xbd71bcac,0x3d753c95,0xbd78bc79,0x3d553d0e,0xbd5cbd04,0x3d623cf1,0xbd67bcdb,0x3d353d35,0xbd3ebd2c,0x3d463d22,0xbd4ebd18,
0x3d0e3d55,0xbd18bd4e,0x3d223d46,0xbd2cbd3e,0x3cc43d6d,0xbcdbbd67,0x3cf13d62,0xbd04bd5c,0x3c483d7b,0xbc79bd78,0x3c953d75,0xbcacbd71,0x3d80,0xbb49bd80,0x3bc93d7f,0xbc16bd7d,
0xbd800000,0x3c16bd7d,0x3d753c95,0xbcdb3d67,0xbd55bd0e,0x3d2cbd3e,0x3d223d46,0xbd5c3d04,0xbcc4bd6d,0x3d78bc79,0x3bc93d7f,0xbd80bb49,0x3c48bd7b,0x3d713cac,0xbcf13d62,0xbd4ebd18,
0x3d35bd35,0x3d183d4e,0xbd623cf1,0xbcacbd71,0x3d7bbc48,0x3b493d80,0xbd7fbbc9,0x3c79bd78,0x3d6d3cc4,0xbd043d5c,0xbd46bd22,0x3d3ebd2c,0x3d0e3d55,0xbd673cdb,0xbc95bd75,0x3d7dbc16,
0xbc48bd7b,0x3d7d3c16,0xbcf13d62,0xbd2cbd3e,0xbd800000,0x3cacbd71,0x3d463d22,0xbd5c3d04,0x3d0e3d55,0xbd783c79,0x3bc9bd7f,0x3d673cdb,0x3d6dbcc4,0x3b493d80,0xbd75bc95,0x3d18bd4e,
0xbd55bd0e,0x3d4ebd18,0x3c953d75,0xbd80bb49,0xbd353d35,0xbcdbbd67,0x3d7fbbc9,0xbc793d78,0x3d7b3c48,0xbd043d5c,0xbd22bd46,0x3d71bcac,0x3cc4bd6d,0x3d3e3d2c,0xbd623cf1,0xbc16bd7d,
0x3cc43d6d,0xbd7dbc16,0x3d22bd46,0x3cac3d71,0xbd7bbc48,0x3d2cbd3e,0x3c953d75,0xbd78bc79,0xbd800000,0x3d04bd5c,0x3cf13d62,0xbd80bb49,0x3d0ebd55,0x3cdb3d67,0xbd7fbbc9,0x3d18bd4e,
0xbd6dbcc4,0x3d4ebd18,0x3bc93d7f,0xbd67bcdb,0x3d55bd0e,0x3b493d80,0xbd62bcf1,0x3d5cbd04,0x3d35bd35,0x3c793d78,0xbd75bc95,0x3d3ebd2c,0x3c483d7b,0xbd71bcac,0x3d46bd22,0x3c163d7d,
0x3d55bd0e,0xbc163d7d,0xbd22bd46,0x3d803b49,0xbd6d3cc4,0x3cacbd71,0x3cf13d62,0xbd78bc79,0x3d7bbc48,0xbd043d5c,0xbc95bd75,0x3d673cdb,0xbd800000,0x3d2cbd3e,0x3bc93d7f,0xbd4ebd18,
0x3c48bd7b,0x3d183d4e,0xbd7fbbc9,0x3d3ebd2c,0xbcc43d6d,0xbcdbbd67,0x3d753c95,0xbd5c3d04,0x3d0ebd55,0x3c793d78,0xbd62bcf1,0x3d71bcac,0xbd353d35,0xbb49bd80,0x3d463d22,0xbd7d3c16,
0x3d35bd35,0xbc163d7d,0xbcf1bd62,0x3d673cdb,0xbd7b3c48,0x3d2cbd3e,0xbbc93d7f,0xbd04bd5c,0x3d6d3cc4,0xbd783c79,0x3d22bd46,0xbb493d80,0xbd0ebd55,0x3d713cac,0xbd753c95,0x3d18bd4e,
0xbd800000,0x3d4ebd18,0xbc953d75,0xbcacbd71,0x3d553d0e,0xbd803b49,0x3d46bd22,0xbc793d78,0xbcc4bd6d,0x3d5c3d04,0xbd7f3bc9,0x3d3ebd2c,0xbc483d7b,0xbcdbbd67,0x3d623cf1,0xbd7d3c16,
0x3d553d0e,0xbd7dbc16,0x3d75bc95,0xbd3e3d2c,0xbd353d35,0x3cacbd71,0x3bc93d7f,0xbd04bd5c,0xbd7bbc48,0x3d78bc79,0xbd463d22,0x3cdbbd67,0x3cc4bd6d,0x3b493d80,0xbcf1bd62,0x3d4e3d18,
0x3c483d7b,0xbd18bd4e,0x3d623cf1,0xbd80bb49,0xbd800000,0x3d67bcdb,0xbd223d46,0x3c79bd78,0xbd0ebd55,0x3d5c3d04,0xbd7fbbc9,0x3d71bcac,0x3d6dbcc4,0xbd2c3d3e,0x3c95bd75,0x3c163d7d,
0xbd6dbcc4,0x3d7d3c16,0xbd7f3bc9,0x3d71bcac,0xbd553d0e,0x3d2cbd3e,0xbcf13d62,0x3c79bd78,0x3d35bd35,0xbd043d5c,0x3c95bd75,0xbb493d80,0xbc48bd7b,0x3cdb3d67,0xbd22bd46,0x3d4e3d18,
0x3cc43d6d,0xbd18bd4e,0x3d463d22,0xbd67bcdb,0x3d7b3c48,0xbd803b49,0x3d75bc95,0xbd5c3d04,0xbd800000,0x3d78bc79,0xbd623cf1,0x3d3ebd2c,0xbd0e3d55,0x3cacbd71,0xbbc93d7f,0xbc16bd7d,
0xbc483d7b,0x3c16bd7d,0xbbc93d7f,0x3b49bd80,0xbcc43d6d,0x3cacbd71,0xbc953d75,0x3c79bd78,0xbd0e3d55,0x3d04bd5c,0xbcf13d62,0x3cdbbd67,0xbd353d35,0x3d2cbd3e,0xbd223d46,0x3d18bd4e,
0xbd553d0e,0x3d4ebd18,0xbd463d22,0x3d3ebd2c,0xbd6d3cc4,0x3d67bcdb,0xbd623cf1,0x3d5cbd04,0xbd7b3c48,0x3d78bc79,0xbd753c95,0x3d71bcac,0xbd800000,0x3d80bb49,0xbd7f3bc9,0x3d7dbc16,
0x3d80,0x3c16bd7d,0xbc953d75,0x3cdbbd67,0xbd0e3d55,0x3d2cbd3e,0xbd463d22,0x3d5cbd04,0xbd6d3cc4,0x3d78bc79,0xbd7f3bc9,0x3d803b49,0xbd7bbc48,0x3d713cac,0xbd62bcf1,0x3d4e3d18,
0xbd35bd35,0x3d183d4e,0xbcf1bd62,0x3cac3d71,0xbc48bd7b,0x3b493d80,0x3bc9bd7f,0xbc793d78,0x3cc4bd6d,0xbd043d5c,0x3d22bd46,0xbd3e3d2c,0x3d55bd0e,0xbd673cdb,0x3d75bc95,0xbd7d3c16,
0xbd7b3c48,0x3d7d3c16,0xbd62bcf1,0x3d2c3d3e,0x3d80,0x3cacbd71,0xbd223d46,0x3d5cbd04,0x3d55bd0e,0xbd783c79,0x3d7f3bc9,0xbd67bcdb,0xbcc4bd6d,0x3b493d80,0x3c95bd75,0xbd183d4e,
0xbd0e3d55,0x3d4ebd18,0xbd753c95,0x3d803b49,0x3d353d35,0xbcdbbd67,0x3bc93d7f,0x3c79bd78,0x3c48bd7b,0xbd043d5c,0x3d46bd22,0xbd713cac,0xbd6dbcc4,0x3d3e3d2c,0xbcf1bd62,0x3c163d7d,
0x3d6dbcc4,0xbd7dbc16,0x3d463d22,0xbcacbd71,0xbc483d7b,0x3d2cbd3e,0xbd753c95,0x3d783c79,0x3d80,0x3d04bd5c,0xbd623cf1,0x3d803b49,0xbd55bd0e,0x3cdb3d67,0x3bc9bd7f,0xbd183d4e,
0xbcc43d6d,0x3d4ebd18,0xbd7f3bc9,0x3d673cdb,0xbd0ebd55,0x3b493d80,0x3cf1bd62,0xbd5c3d04,0xbd35bd35,0x3c793d78,0x3c95bd75,0xbd3e3d2c,0x3d7bbc48,0xbd71bcac,0x3d223d46,0xbc16bd7d,
0xbd0ebd55,0xbc163d7d,0x3d46bd22,0xbd80bb49,0x3cc43d6d,0x3cacbd71,0xbd623cf1,0x3d783c79,0xbc48bd7b,0xbd043d5c,0x3d75bc95,0xbd67bcdb,0x3d80,0x3d2cbd3e,0xbd7f3bc9,0x3d4e3d18,
0xbd7bbc48,0x3d183d4e,0x3bc9bd7f,0xbd3e3d2c,0x3d6d3cc4,0xbcdbbd67,0xbc953d75,0x3d5cbd04,0xbd55bd0e,0x3c793d78,0x3cf1bd62,0xbd713cac,0x3d353d35,0xbb49bd80,0xbd223d46,0x3d7dbc16,
0xbd35bd35,0xbc163d7d,0x3d62bcf1,0xbd67bcdb,0x3c483d7b,0x3d2cbd3e,0xbd7fbbc9,0x3d043d5c,0x3cc4bd6d,0xbd783c79,0x3d463d22,0x3b49bd80,0xbd553d0e,0x3d713cac,0xbc95bd75,0xbd183d4e,
0x3d80,0x3d4ebd18,0xbd75bc95,0x3cac3d71,0x3d0ebd55,0xbd803b49,0x3d223d46,0x3c79bd78,0xbd6d3cc4,0x3d5c3d04,0xbbc9bd7f,0xbd3e3d2c,0x3d7b3c48,0xbcdbbd67,0xbcf13d62,0x3d7dbc16,
0x3d0ebd55,0xbd7dbc16,0x3c953d75,0x3d3ebd2c,0x3d353d35,0x3cacbd71,0xbd7f3bc9,0x3d043d5c,0xbc483d7b,0x3d78bc79,0xbd22bd46,0xbcdb3d67,0xbd6dbcc4,0x3b493d80,0x3d62bcf1,0xbd4ebd18,
0x3d7bbc48,0xbd18bd4e,0xbcf13d62,0x3d803b49,0x3d80,0x3d67bcdb,0xbd46bd22,0xbc793d78,0xbd553d0e,0x3d5c3d04,0x3bc9bd7f,0xbd713cac,0xbcc4bd6d,0xbd2c3d3e,0x3d753c95,0xbc16bd7d,
0xbcc43d6d,0x3d7d3c16,0xbbc9bd7f,0xbd713cac,0x3d0e3d55,0x3d2cbd3e,0xbd62bcf1,0xbc793d78,0xbd35bd35,0xbd043d5c,0x3d753c95,0x3b49bd80,0xbd7b3c48,0x3cdb3d67,0x3d46bd22,0xbd4ebd18,
0x3d6dbcc4,0xbd18bd4e,0xbd223d46,0x3d673cdb,0x3c48bd7b,0xbd803b49,0x3c953d75,0x3d5cbd04,0x3d80,0x3d78bc79,0xbcf1bd62,0xbd3e3d2c,0x3d553d0e,0x3cacbd71,0xbd7fbbc9,0x3c163d7d,
0x3d7b3c48,0x3c16bd7d,0xbd7fbbc9,0xbb493d80,0x3d6d3cc4,0x3cacbd71,0xbd75bc95,0xbc793d78,0x3d553d0e,0x3d04bd5c,0xbd62bcf1,0xbcdb3d67,0x3d353d35,0x3d2cbd3e,0xbd46bd22,0xbd183d4e,
0x3d0e3d55,0x3d4ebd18,0xbd22bd46,0xbd3e3d2c,0x3cc43d6d,0x3d67bcdb,0xbcf1bd62,0xbd5c3d04,0x3c483d7b,0x3d78bc79,0xbc95bd75,0xbd713cac,0x3d80,0x3d80bb49,0xbbc9bd7f,0xbd7d3c16,
0xbd800000,0x3d7d3c16,0xbd75bc95,0x3d673cdb,0xbd55bd0e,0x3d3e3d2c,0xbd22bd46,0x3d043d5c,0xbcc4bd6d,0x3c793d78,0xbbc9bd7f,0xbb493d80,0x3c48bd7b,0xbcac3d71,0x3cf1bd62,0xbd183d4e,
0x3d35bd35,0xbd4e3d18,0x3d62bcf1,0xbd713cac,0x3d7bbc48,0xbd803b49,0x3d7f3bc9,0xbd78bc79,0x3d6d3cc4,0xbd5cbd04,0x3d463d22,0xbd2cbd3e,0x3d0e3d55,0xbcdbbd67,0x3c953d75,0xbc16bd7d,
0xbc48bd7b,0xbc163d7d,0x3cf1bd62,0xbd3e3d2c,0xbd800000,0x3d713cac,0xbd46bd22,0x3d043d5c,0x3d0e3d55,0xbc79bd78,0xbbc93d7f,0x3cdbbd67,0x3d6dbcc4,0xbd803b49,0x3d753c95,0xbd4ebd18,
0xbd55bd0e,0x3d183d4e,0xbc95bd75,0xbb493d80,0xbd353d35,0x3d67bcdb,0xbd7f3bc9,0x3d783c79,0x3d7b3c48,0xbd5cbd04,0x3d223d46,0xbcacbd71,0x3cc4bd6d,0xbd2c3d3e,0x3d62bcf1,0xbd7d3c16,
0x3cc43d6d,0x3c16bd7d,0xbd223d46,0x3d71bcac,0xbd7bbc48,0x3d3e3d2c,0xbc95bd75,0xbc793d78,0xbd800000,0x3d5c3d04,0xbcf1bd62,0xbb493d80,0x3d0ebd55,0xbd673cdb,0x3d7f3bc9,0xbd4ebd18,
0xbd6dbcc4,0x3d183d4e,0xbbc9bd7f,0xbcdb3d67,0x3d55bd0e,0xbd803b49,0x3d623cf1,0xbd04bd5c,0x3d35bd35,0xbd783c79,0x3d753c95,0xbd2cbd3e,0x3c483d7b,0x3cacbd71,0xbd463d22,0x3d7dbc16,
0x3d55bd0e,0xbd7dbc16,0x3d223d46,0x3b49bd80,0xbd6d3cc4,0x3d713cac,0xbcf1bd62,0xbc793d78,0x3d7bbc48,0xbd5cbd04,0x3c953d75,0x3cdbbd67,0xbd800000,0x3d3e3d2c,0xbbc9bd7f,0xbd183d4e,
0x3c48bd7b,0xbd4e3d18,0x3d7f3bc9,0xbd2cbd3e,0xbcc43d6d,0x3d67bcdb,0xbd75bc95,0x3d043d5c,0x3d0ebd55,0xbd783c79,0x3d623cf1,0xbcacbd71,0xbd353d35,0x3d80bb49,0xbd46bd22,0x3c163d7d,
0x3d35bd35,0xbd7dbc16,0x3cf13d62,0x3cdbbd67,0xbd7b3c48,0x3d3e3d2c,0x3bc9bd7f,0xbd5c3d04,0x3d6d3cc4,0xbc79bd78,0xbd223d46,0x3d803b49,0xbd0ebd55,0xbcac3d71,0x3d75bc95,0xbd4ebd18,
0xbd800000,0x3d183d4e,0x3c95bd75,0xbd713cac,0x3d553d0e,0xbb49bd80,0xbd463d22,0x3d783c79,0xbcc4bd6d,0xbd043d5c,0x3d7fbbc9,0xbd2cbd3e,0xbc483d7b,0x3d67bcdb,0xbd62bcf1,0x3c163d7d,
0x3d553d0e,0x3c16bd7d,0xbd753c95,0x3d2c3d3e,0xbd353d35,0x3d713cac,0xbbc9bd7f,0xbd5c3d04,0xbd7bbc48,0x3c793d78,0x3d46bd22,0xbd67bcdb,0x3cc4bd6d,0xbd803b49,0x3cf13d62,0x3d18bd4e,
0x3c483d7b,0x3d4ebd18,0xbd62bcf1,0xbb493d80,0xbd800000,0x3cdb3d67,0x3d22bd46,0xbd78bc79,0xbd0ebd55,0xbd043d5c,0x3d7f3bc9,0xbcacbd71,0x3d6dbcc4,0xbd3ebd2c,0xbc953d75,0x3d7dbc16,
0xbd6dbcc4,0xbc163d7d,0x3d7fbbc9,0xbcacbd71,0xbd553d0e,0x3d3e3d2c,0x3cf1bd62,0xbd78bc79,0x3d35bd35,0xbd5cbd04,0xbc953d75,0x3d803b49,0xbc48bd7b,0xbd673cdb,0x3d223d46,0x3d18bd4e,
0x3cc43d6d,0x3d4ebd18,0xbd46bd22,0xbcdb3d67,0x3d7b3c48,0xbb49bd80,0xbd753c95,0x3d043d5c,0xbd800000,0x3c793d78,0x3d62bcf1,0xbd2cbd3e,0xbd0e3d55,0x3d713cac,0x3bc9bd7f,0xbd7d3c16,
0xbc483d7b,0x3d7d3c16,0x3bc9bd7f,0xbd80bb49,0xbcc43d6d,0x3d713cac,0x3c95bd75,0xbd78bc79,0xbd0e3d55,0x3d5c3d04,0x3cf1bd62,0xbd67bcdb,0xbd353d35,0x3d3e3d2c,0x3d22bd46,0xbd4ebd18,
0xbd553d0e,0x3d183d4e,0x3d46bd22,0xbd2cbd3e,0xbd6d3cc4,0x3cdb3d67,0x3d62bcf1,0xbd04bd5c,0xbd7b3c48,0x3c793d78,0x3d75bc95,0xbcacbd71,0xbd800000,0x3b493d80,0x3d7fbbc9,0xbc16bd7d,
0x3d80,0x3d7d3c16,0x3c95bd75,0xbd67bcdb,0xbd0e3d55,0x3d3e3d2c,0x3d46bd22,0xbd04bd5c,0xbd6d3cc4,0x3c793d78,0x3d7fbbc9,0x3b49bd80,0xbd7bbc48,0xbcac3d71,0x3d623cf1,0x3d18bd4e,
0xbd35bd35,0xbd4e3d18,0x3cf13d62,0x3d71bcac,0xbc48bd7b,0xbd803b49,0xbbc93d7f,0x3d783c79,0x3cc4bd6d,0xbd5cbd04,0xbd223d46,0x3d2c3d3e,0x3d55bd0e,0xbcdbbd67,0xbd753c95,0x3c163d7d,
0xbd7b3c48,0xbc163d7d,0x3d623cf1,0x3d3ebd2c,0x3d80,0x3d713cac,0x3d22bd46,0xbd04bd5c,0x3d55bd0e,0xbc79bd78,0xbd7fbbc9,0xbcdb3d67,0xbcc4bd6d,0xbd803b49,0xbc953d75,0x3d4e3d18,
0xbd0e3d55,0x3d183d4e,0x3d75bc95,0x3b49bd80,0x3d353d35,0x3d67bcdb,0xbbc9bd7f,0xbd78bc79,0x3c48bd7b,0xbd5cbd04,0xbd463d22,0x3cac3d71,0xbd6dbcc4,0xbd2c3d3e,0x3cf13d62,0x3d7dbc16,
0x3d6dbcc4,0x3c16bd7d,0xbd46bd22,0xbd713cac,0xbc483d7b,0x3d3e3d2c,0x3d75bc95,0x3c79bd78,0x3d80,0x3d5c3d04,0x3d62bcf1,0x3b49bd80,0xbd55bd0e,0xbd673cdb,0xbbc93d7f,0x3d4e3d18,
0xbcc43d6d,0x3d183d4e,0x3d7fbbc9,0x3cdbbd67,0xbd0ebd55,0xbd803b49,0xbcf13d62,0x3d043d5c,0xbd35bd35,0xbd783c79,0xbc953d75,0x3d2c3d3e,0x3d7bbc48,0x3cacbd71,0xbd22bd46,0xbd7d3c16,
0xbd0ebd55,0xbd7dbc16,0xbd463d22,0xbb493d80,0x3cc43d6d,0x3d713cac,0x3d62bcf1,0x3c79bd78,0xbc48bd7b,0xbd5cbd04,0xbd753c95,0xbcdb3d67,0x3d80,0x3d3e3d2c,0x3d7fbbc9,0x3d18bd4e,
0xbd7bbc48,0xbd4e3d18,0xbbc93d7f,0x3d2c3d3e,0x3d6d3cc4,0x3d67bcdb,0x3c95bd75,0xbd04bd5c,0xbd55bd0e,0xbd783c79,0xbcf13d62,0x3cac3d71,0x3d353d35,0x3d80bb49,0x3d22bd46,0xbc16bd7d,
0xbd35bd35,0xbd7dbc16,0xbd623cf1,0xbcdb3d67,0x3c483d7b,0x3d3e3d2c,0x3d7f3bc9,0x3d5cbd04,0x3cc4bd6d,0xbc79bd78,0xbd46bd22,0xbd80bb49,0xbd553d0e,0xbcac3d71,0x3c953d75,0x3d4e3d18,
0x3d80,0x3d183d4e,0x3d753c95,0x3d71bcac,0x3d0ebd55,0xbb49bd80,0xbd22bd46,0xbd78bc79,0xbd6d3cc4,0xbd043d5c,0x3bc93d7f,0x3d2c3d3e,0x3d7b3c48,0x3d67bcdb,0x3cf1bd62,0xbc16bd7d,
0x3d0ebd55,0x3c16bd7d,0xbc95bd75,0xbd2cbd3e,0x3d353d35,0x3d713cac,0x3d7fbbc9,0x3d5cbd04,0xbc483d7b,0x3c793d78,0x3d223d46,0x3d673cdb,0xbd6dbcc4,0xbd803b49,0xbd623cf1,0xbd183d4e,
0x3d7bbc48,0x3d4ebd18,0x3cf1bd62,0x3b49bd80,0x3d80,0x3cdb3d67,0x3d463d22,0x3d783c79,0xbd553d0e,0xbd043d5c,0xbbc93d7f,0x3cac3d71,0xbcc4bd6d,0xbd3ebd2c,0xbd75bc95,0xbd7d3c16,
0xbcc43d6d,0xbc163d7d,0x3bc93d7f,0x3cac3d71,0x3d0e3d55,0x3d3e3d2c,0x3d623cf1,0x3d783c79,0xbd35bd35,0xbd5cbd04,0xbd75bc95,0xbd80bb49,0xbd7b3c48,0xbd673cdb,0xbd463d22,0xbd183d4e,
0x3d6dbcc4,0x3d4ebd18,0x3d22bd46,0x3cdbbd67,0x3c48bd7b,0xbb49bd80,0xbc95bd75,0xbd04bd5c,0x3d80,0x3c793d78,0x3cf13d62,0x3d2c3d3e,0x3d553d0e,0x3d713cac,0x3d7f3bc9,0x3d7dbc16,
0x3d7b3c48,0x3d7d3c16,0x3d7f3bc9,0x3d803b49,0x3d6d3cc4,0x3d713cac,0x3d753c95,0x3d783c79,0x3d553d0e,0x3d5c3d04,0x3d623cf1,0x3d673cdb,0x3d353d35,0x3d3e3d2c,0x3d463d22,0x3d4e3d18,
0x3d0e3d55,0x3d183d4e,0x3d223d46,0x3d2c3d3e,0x3cc43d6d,0x3cdb3d67,0x3cf13d62,0x3d043d5c,0x3c483d7b,0x3c793d78,0x3c953d75,0x3cac3d71,0x3d80,0x3b493d80,0x3bc93d7f,0x3c163d7d,
0xbd800000,0xbc163d7d,0x3d753c95,0x3cdbbd67,0xbd55bd0e,0xbd2c3d3e,0x3d223d46,0x3d5cbd04,0xbcc4bd6d,0xbd783c79,0x3bc93d7f,0x3d803b49,0x3c48bd7b,0xbd71bcac,0xbcf13d62,0x3d4e3d18,
0x3d35bd35,0xbd18bd4e,0xbd623cf1,0x3cac3d71,0x3d7bbc48,0xbb49bd80,0xbd7fbbc9,0xbc793d78,0x3d6d3cc4,0x3d04bd5c,0xbd46bd22,0xbd3e3d2c,0x3d0e3d55,0x3d67bcdb,0xbc95bd75,0xbd7d3c16,
0xbc48bd7b,0xbd7dbc16,0xbcf13d62,0x3d2c3d3e,0xbd800000,0xbcac3d71,0x3d463d22,0x3d5cbd04,0x3d0e3d55,0x3d78bc79,0x3bc9bd7f,0xbd67bcdb,0x3d6dbcc4,0xbb49bd80,0xbd75bc95,0xbd183d4e,
0xbd55bd0e,0xbd4e3d18,0x3c953d75,0x3d803b49,0xbd353d35,0x3cdb3d67,0x3d7fbbc9,0x3c79bd78,0x3d7b3c48,0x3d04bd5c,0xbd22bd46,0xbd713cac,0x3cc4bd6d,0xbd3ebd2c,0xbd623cf1,0x3c163d7d,
0x3cc43d6d,0x3d7d3c16,0x3d22bd46,0xbcacbd71,0xbd7bbc48,0xbd2c3d3e,0x3c953d75,0x3d783c79,0xbd800000,0xbd043d5c,0x3cf13d62,0x3d803b49,0x3d0ebd55,0xbcdbbd67,0xbd7fbbc9,0xbd183d4e,
0xbd6dbcc4,0xbd4e3d18,0x3bc93d7f,0x3d673cdb,0x3d55bd0e,0xbb49bd80,0xbd62bcf1,0xbd5c3d04,0x3d35bd35,0xbc79bd78,0xbd75bc95,0xbd3e3d2c,0x3c483d7b,0x3d713cac,0x3d46bd22,0xbc16bd7d,
0x3d55bd0e,0x3c16bd7d,0xbd22bd46,0xbd80bb49,0xbd6d3cc4,0xbcac3d71,0x3cf13d62,0x3d783c79,0x3d7bbc48,0x3d04bd5c,0xbc95bd75,0xbd67bcdb,0xbd800000,0xbd2c3d3e,0x3bc93d7f,0x3d4e3d18,
0x3c48bd7b,0xbd18bd4e,0xbd7fbbc9,0xbd3e3d2c,0xbcc43d6d,0x3cdb3d67,0x3d753c95,0x3d5cbd04,0x3d0ebd55,0xbc79bd78,0xbd62bcf1,0xbd713cac,0xbd353d35,0x3b493d80,0x3d463d22,0x3d7dbc16,
0x3d35bd35,0x3c16bd7d,0xbcf1bd62,0xbd67bcdb,0xbd7b3c48,0xbd2c3d3e,0xbbc93d7f,0x3d043d5c,0x3d6d3cc4,0x3d78bc79,0x3d22bd46,0x3b49bd80,0xbd0ebd55,0xbd71bcac,0xbd753c95,0xbd183d4e,
0xbd800000,0xbd4e3d18,0xbc953d75,0x3cac3d71,0x3d553d0e,0x3d80bb49,0x3d46bd22,0x3c79bd78,0xbcc4bd6d,0xbd5cbd04,0xbd7f3bc9,0xbd3e3d2c,0xbc483d7b,0x3cdb3d67,0x3d623cf1,0x3d7dbc16,
0x3d553d0e,0x3d7d3c16,0x3d75bc95,0x3d3ebd2c,0xbd353d35,0xbcac3d71,0x3bc93d7f,0x3d043d5c,0xbd7bbc48,0xbd783c79,0xbd463d22,0xbcdb3d67,0x3cc4bd6d,0xbb49bd80,0xbcf1bd62,0xbd4ebd18,
0x3c483d7b,0x3d183d4e,0x3d623cf1,0x3d803b49,0xbd800000,0xbd673cdb,0xbd223d46,0xbc793d78,0xbd0ebd55,0xbd5cbd04,0xbd7fbbc9,0xbd713cac,0x3d6dbcc4,0x3d2cbd3e,0x3c95bd75,0xbc16bd7d,
0xbd6dbcc4,0xbd7dbc16,0xbd7f3bc9,0xbd713cac,0xbd553d0e,0xbd2c3d3e,0xbcf13d62,0xbc793d78,0x3d35bd35,0x3d04bd5c,0x3c95bd75,0x3b49bd80,0xbc48bd7b,0xbcdbbd67,0xbd22bd46,0xbd4ebd18,
0x3cc43d6d,0x3d183d4e,0x3d463d22,0x3d673cdb,0x3d7b3c48,0x3d80bb49,0x3d75bc95,0x3d5cbd04,0xbd800000,0xbd783c79,0xbd623cf1,0xbd3e3d2c,0xbd0e3d55,0xbcac3d71,0xbbc93d7f,0x3c163d7d,
0xbc483d7b,0xbc163d7d,0xbbc93d7f,0xbb493d80,0xbcc43d6d,0xbcac3d71,0xbc953d75,0xbc793d78,0xbd0e3d55,0xbd043d5c,0xbcf13d62,0xbcdb3d67,0xbd353d35,0xbd2c3d3e,0xbd223d46,0xbd183d4e,
0xbd553d0e,0xbd4e3d18,0xbd463d22,0xbd3e3d2c,0xbd6d3cc4,0xbd673cdb,0xbd623cf1,0xbd5c3d04,0xbd7b3c48,0xbd783c79,0xbd753c95,0xbd713cac,0xbd800000,0xbd803b49,0xbd7f3bc9,0xbd7d3c16,
0x3f003f00,0xbf003f00,0x3f003f00,0xbf003f00,0x3f003f00,0xbf003f00,0x3f003f00,0xbf003f00,0x3f003f00,0xbf003f00,0x3f003f00,0xbf003f00,0x3f003f00,0xbf003f00,0x3f003f00,0xbf003f00,
0x3eff3f00,0xbd490000,0x3ea23eb5,0xbec6beb5,0x3ef53efb,0xbe15bdc8,0x3e713e8e,0xbee2bed5,0x3ee23eed,0xbe71be44,0x3e153e44,0xbef5beed,0x3ec63ed5,0xbea2be8e,0x3d493dc8,0xbeffbefb,
0x3efb3f00,0xbdc80000,0xbdc80000,0xbefbbf00,0x3ed53eed,0xbe8ebe44,0xbe8ebe44,0xbed5beed,0x3e8e3eb5,0xbed5beb5,0xbed5beb5,0xbe8ebeb5,0x3dc83e44,0xbefbbeed,0xbefbbeed,0xbdc8be44,
0x3ef53f00,0xbe150000,0xbee2beb5,0xbe71beb5,0x3ea23ed5,0xbec6be8e,0xbeffbefb,0x3d49bdc8,0x3d493e44,0xbeffbeed,0xbec6beed,0x3ea23e44,0xbe71bdc8,0xbee2befb,0xbe15be8e,0x3ef53ed5,
0x3eed3f00,0xbe440000,0xbeedbf00,0x3e440000,0x3e443eb5,0xbeedbeb5,0xbe44beb5,0x3eed3eb5,0xbe440000,0xbeedbf00,0x3e440000,0x3eed3f00,0xbeedbeb5,0xbe44beb5,0x3eed3eb5,0x3e443eb5,
0x3ee23f00,0xbe710000,0xbe15beb5,0x3ef53eb5,0x3d493e8e,0xbeffbed5,0x3ea23dc8,0x3ec63efb,0xbec6be44,0xbea2beed,0x3eff3eed,0xbd493e44,0xbef5befb,0x3e15bdc8,0x3e713ed5,0xbee2be8e,
0x3ed53f00,0xbe8e0000,0x3e8e0000,0x3ed53f00,0xbdc83e44,0xbefbbeed,0x3efb3eed,0xbdc83e44,0xbefbbeb5,0xbdc8beb5,0x3dc83eb5,0xbefbbeb5,0xbe8ebeed,0x3ed53e44,0xbed5be44,0xbe8ebeed,
0x3ec63f00,0xbea20000,0x3eff3eb5,0x3d493eb5,0xbe713dc8,0xbee2befb,0x3e153ed5,0xbef5be8e,0xbef5beed,0x3e15be44,0xbee2be44,0xbe71beed,0x3d49be8e,0x3eff3ed5,0xbea2befb,0x3ec63dc8,
0x3f00,0xbf000000,0x3f00,0xbf000000,0xbf00,0x3f000000,0xbf00,0x3f000000,0x3f00,0xbf000000,0x3f00,0xbf000000,0xbf00,0x3f000000,0xbf00,0x3f000000,
0xbd493f00,0xbeff0000,0xbec63eb5,0xbea2beb5,0x3e15befb,0x3ef53dc8,0x3ee2be8e,0x3e713ed5,0xbe713eed,0xbee2be44,0xbef53e44,0xbe15beed,0x3ea2bed5,0x3ec63e8e,0x3effbdc8,0x3d493efb,
0xbdc83f00,0xbefb0000,0xbefb0000,0x3dc8bf00,0x3e8ebeed,0x3ed53e44,0x3ed53e44,0xbe8e3eed,0xbed53eb5,0xbe8ebeb5,0xbe8ebeb5,0x3ed5beb5,0x3efbbe44,0x3dc83eed,0x3dc83eed,0xbefb3e44,
0xbe153f00,0xbef50000,0xbe71beb5,0x3ee2beb5,0x3ec6bed5,0x3ea23e8e,0xbd493efb,0xbeff3dc8,0xbeff3e44,0xbd49beed,0x3ea2beed,0x3ec63e44,0x3ee23dc8,0xbe713efb,0xbef53e8e,0xbe15bed5,
0xbe443f00,0xbeed0000,0x3e44bf00,0x3eed0000,0x3eedbeb5,0x3e443eb5,0xbeed3eb5,0xbe44beb5,0xbeed0000,0x3e44bf00,0x3eed0000,0xbe443f00,0x3e443eb5,0xbeed3eb5,0xbe44beb5,0x3eedbeb5,
0xbe713f00,0xbee20000,0x3ef5beb5,0x3e153eb5,0x3effbe8e,0x3d493ed5,0xbec6bdc8,0x3ea2befb,0xbea2be44,0x3ec6beed,0xbd493eed,0xbeff3e44,0xbe153efb,0xbef53dc8,0x3ee2bed5,0x3e713e8e,
0xbe8e3f00,0xbed50000,0x3ed50000,0xbe8e3f00,0x3efbbe44,0xbdc83eed,0x3dc8beed,0x3efbbe44,0xbdc8beb5,0x3efbbeb5,0xbefb3eb5,0xbdc8beb5,0xbed53eed,0xbe8ebe44,0x3e8e3e44,0xbed53eed,
0xbea23f00,0xbec60000,0x3d493eb5,0xbeff3eb5,0x3ee2bdc8,0xbe713efb,0x3ef5bed5,0x3e153e8e,0x3e15beed,0x3ef5be44,0xbe71be44,0x3ee2beed,0xbeff3e8e,0x3d49bed5,0xbec63efb,0xbea2bdc8,
0x3eb53f00,0xbeb50000,0x3eb53f00,0xbeb50000,0xbeb50000,0xbeb5bf00,0xbeb50000,0xbeb5bf00,0xbeb5bf00,0x3eb50000,0xbeb5bf00,0x3eb50000,0x3eb50000,0x3eb53f00,0x3eb50000,0x3eb53f00,
0xbeff3f00,0x3d490000,0xbea23eb5,0x3ec6beb5,0xbef53efb,0x3e15bdc8,0xbe713e8e,0x3ee2bed5,0xbee23eed,0x3e71be44,0xbe153e44,0x3ef5beed,0xbec63ed5,0x3ea2be8e,0xbd493dc8,0x3effbefb,
0xbefb3f00,0x3dc80000,0x3dc80000,0x3efbbf00,0xbed53eed,0x3e8ebe44,0x3e8ebe44,0x3ed5beed,0xbe8e3eb5,0x3ed5beb5,0x3ed5beb5,0x3e8ebeb5,0xbdc83e44,0x3efbbeed,0x3efbbeed,0x3dc8be44,
0xbef53f00,0x3e150000,0x3ee2beb5,0x3e71beb5,0xbea23ed5,0x3ec6be8e,0x3effbefb,0xbd49bdc8,0xbd493e44,0x3effbeed,0x3ec6beed,0xbea23e44,0x3e71bdc8,0x3ee2befb,0x3e15be8e,0xbef53ed5,
0xbeed3f00,0x3e440000,0x3eedbf00,0xbe440000,0xbe443eb5,0x3eedbeb5,0x3e44beb5,0xbeed3eb5,0x3e440000,0x3eedbf00,0xbe440000,0xbeed3f00,0x3eedbeb5,0x3e44beb5,0xbeed3eb5,0xbe443eb5,
0xbee23f00,0x3e710000,0x3e15beb5,0xbef53eb5,0xbd493e8e,0x3effbed5,0xbea23dc8,0xbec63efb,0x3ec6be44,0x3ea2beed,0xbeff3eed,0x3d493e44,0x3ef5befb,0xbe15bdc8,0xbe713ed5,0x3ee2be8e,
0xbed53f00,0x3e8e0000,0xbe8e0000,0xbed53f00,0x3dc83e44,0x3efbbeed,0xbefb3eed,0x3dc83e44,0x3efbbeb5,0x3dc8beb5,0xbdc83eb5,0x3efbbeb5,0x3e8ebeed,0xbed53e44,0x3ed5be44,0x3e8ebeed,
0xbec63f00,0x3ea20000,0xbeff3eb5,0xbd493eb5,0x3e713dc8,0x3ee2befb,0xbe153ed5,0x3ef5be8e,0x3ef5beed,0xbe15be44,0x3ee2be44,0x3e71beed,0xbd49be8e,0xbeff3ed5,0x3ea2befb,0xbec63dc8,
0xbeb53f00,0xbeb50000,0xbeb53f00,0xbeb50000,0x3eb50000,0xbeb53f00,0x3eb50000,0xbeb53f00,0x3eb5bf00,0x3eb50000,0x3eb5bf00,0x3eb50000,0xbeb50000,0x3eb5bf00,0xbeb50000,0x3eb5bf00,
0x3d493f00,0x3eff0000,0x3ec63eb5,0x3ea2beb5,0xbe15befb,0xbef53dc8,0xbee2be8e,0xbe713ed5,0x3e713eed,0x3ee2be44,0x3ef53e44,0x3e15beed,0xbea2bed5,0xbec63e8e,0xbeffbdc8,0xbd493efb,
0x3dc83f00,0x3efb0000,0x3efb0000,0xbdc8bf00,0xbe8ebeed,0xbed53e44,0xbed53e44,0x3e8e3eed,0x3ed53eb5,0x3e8ebeb5,0x3e8ebeb5,0xbed5beb5,0xbefbbe44,0xbdc83eed,0xbdc83eed,0x3efb3e44,
0x3e153f00,0x3ef50000,0x3e71beb5,0xbee2beb5,0xbec6bed5,0xbea23e8e,0x3d493efb,0x3eff3dc8,0x3eff3e44,0x3d49beed,0xbea2beed,0xbec63e44,0xbee23dc8,0x3e713efb,0x3ef53e8e,0x3e15bed5,
0x3e443f00,0x3eed0000,0xbe44bf00,0xbeed0000,0xbeedbeb5,0xbe443eb5,0x3eed3eb5,0x3e44beb5,0x3eed0000,0xbe44bf00,0xbeed0000,0x3e443f00,0xbe443eb5,0x3eed3eb5,0x3e44beb5,0xbeedbeb5,
0x3e713f00,0x3ee20000,0xbef5beb5,0xbe153eb5,0xbeffbe8e,0xbd493ed5,0x3ec6bdc8,0xbea2befb,0x3ea2be44,0xbec6beed,0x3d493eed,0x3eff3e44,0x3e153efb,0x3ef53dc8,0xbee2bed5,0xbe713e8e,
0x3e8e3f00,0x3ed50000,0xbed50000,0x3e8e3f00,0xbefbbe44,0x3dc83eed,0xbdc8beed,0xbefbbe44,0x3dc8beb5,0xbefbbeb5,0x3efb3eb5,0x3dc8beb5,0x3ed53eed,0x3e8ebe44,0xbe8e3e44,0x3ed53eed,
0x3ea23f00,0x3ec60000,0xbd493eb5,0x3eff3eb5,0xbee2bdc8,0x3e713efb,0xbef5bed5,0xbe153e8e,0xbe15beed,0xbef5be44,0x3e71be44,0xbee2beed,0x3eff3e8e,0xbd49bed5,0x3ec63efb,0x3ea2bdc8,
0x3f003f00,0xbf003f00,0x3f003f00,0xbf003f00,0x3f003f00,0xbf003f00,0x3f003f00,0xbf003f00,0x3f003f00,0xbf003f00,0x3f003f00,0xbf003f00,0x3f003f00,0xbf003f00,0x3f003f00,0xbf003f00,
0xbd490000,0xbeffbf00,0xbec6beb5,0xbea2beb5,0xbe15bdc8,0xbef5befb,0xbee2bed5,0xbe71be8e,0xbe71be44,0xbee2beed,0xbef5beed,0xbe15be44,0xbea2be8e,0xbec6bed5,0xbeffbefb,0xbd49bdc8,
0xbefbbf00,0x3dc80000,0x3dc80000,0x3efb3f00,0xbed5beed,0x3e8e3e44,0x3e8e3e44,0x3ed53eed,0xbe8ebeb5,0x3ed53eb5,0x3ed53eb5,0x3e8e3eb5,0xbdc8be44,0x3efb3eed,0x3efb3eed,0x3dc83e44,
0x3e150000,0x3ef53f00,0x3e713eb5,0xbee2beb5,0x3ec63e8e,0x3ea23ed5,0xbd493dc8,0xbeffbefb,0x3eff3eed,0x3d493e44,0xbea2be44,0xbec6beed,0x3ee23efb,0xbe71bdc8,0xbef5bed5,0xbe15be8e,
0x3eed3f00,0xbe440000,0xbeedbf00,0x3e440000,0x3e443eb5,0xbeedbeb5,0xbe44beb5,0x3eed3eb5,0xbe440000,0xbeedbf00,0x3e440000,0x3eed3f00,0xbeedbeb5,0xbe44beb5,0x3eed3eb5,0x3e443eb5,
0xbe710000,0xbee2bf00,0x3ef53eb5,0x3e153eb5,0xbeffbed5,0xbd49be8e,0x3ec63efb,0xbea2bdc8,0xbea2beed,0x3ec63e44,0xbd493e44,0xbeffbeed,0x3e15bdc8,0x3ef53efb,0xbee2be8e,0xbe71bed5,
0xbed5bf00,0x3e8e0000,0xbe8e0000,0xbed5bf00,0x3dc8be44,0x3efb3eed,0xbefbbeed,0x3dc8be44,0x3efb3eb5,0x3dc83eb5,0xbdc8beb5,0x3efb3eb5,0x3e8e3eed,0xbed5be44,0x3ed53e44,0x3e8e3eed,
0x3ea20000,0x3ec63f00,0xbd49beb5,0x3eff3eb5,0x3ee23efb,0xbe713dc8,0x3ef53e8e,0x3e153ed5,0xbe153e44,0xbef5beed,0x3e713eed,0xbee2be44,0xbeffbed5,0x3d49be8e,0xbec6bdc8,0xbea2befb,
0x3f00,0xbf000000,0x3f00,0xbf000000,0xbf00,0x3f000000,0xbf00,0x3f000000,0x3f00,0xbf000000,0x3f00,0xbf000000,0xbf00,0x3f000000,0xbf00,0x3f000000,
0xbeff0000,0x3d49bf00,0xbea2beb5,0x3ec6beb5,0x3ef53dc8,0xbe153efb,0x3e713ed5,0xbee23e8e,0xbee2be44,0x3e71beed,0xbe15beed,0x3ef5be44,0x3ec63e8e,0xbea23ed5,0x3d493efb,0xbeff3dc8,
0x3dc8bf00,0x3efb0000,0x3efb0000,0xbdc83f00,0xbe8e3eed,0xbed5be44,0xbed5be44,0x3e8ebeed,0x3ed5beb5,0x3e8e3eb5,0x3e8e3eb5,0xbed53eb5,0xbefb3e44,0xbdc8beed,0xbdc8beed,0x3efbbe44,
0x3ef50000,0xbe153f00,0xbee23eb5,0xbe71beb5,0xbea2be8e,0x3ec6bed5,0x3effbdc8,0xbd493efb,0x3d493eed,0xbeff3e44,0xbec6be44,0x3ea2beed,0x3e71befb,0x3ee23dc8,0x3e153ed5,0xbef53e8e,
0xbe443f00,0xbeed0000,0x3e44bf00,0x3eed0000,0x3eedbeb5,0x3e443eb5,0xbeed3eb5,0xbe44beb5,0xbeed0000,0x3e44bf00,0x3eed0000,0xbe443f00,0x3e443eb5,0xbeed3eb5,0xbe44beb5,0x3eedbeb5,
0xbee20000,0x3e71bf00,0x3e153eb5,0xbef53eb5,0x3d493ed5,0xbeff3e8e,0x3ea2befb,0x3ec63dc8,0x3ec6beed,0x3ea23e44,0xbeff3e44,0x3d49beed,0xbef53dc8,0x3e15befb,0x3e713e8e,0xbee23ed5,
0x3e8ebf00,0x3ed50000,0xbed50000,0x3e8ebf00,0xbefb3e44,0x3dc8beed,0xbdc83eed,0xbefb3e44,0x3dc83eb5,0xbefb3eb5,0x3efbbeb5,0x3dc83eb5,0x3ed5beed,0x3e8e3e44,0xbe8ebe44,0x3ed5beed,
0x3ec60000,0xbea23f00,0x3effbeb5,0x3d493eb5,0x3e71befb,0x3ee2bdc8,0xbe15be8e,0x3ef5bed5,0xbef53e44,0x3e15beed,0xbee23eed,0xbe71be44,0xbd493ed5,0xbeff3e8e,0x3ea23dc8,0xbec63efb,
0x3eb53f00,0xbeb50000,0x3eb53f00,0xbeb50000,0xbeb50000,0xbeb5bf00,0xbeb50000,0xbeb5bf00,0xbeb5bf00,0x3eb50000,0xbeb5bf00,0x3eb50000,0x3eb50000,0x3eb53f00,0x3eb50000,0x3eb53f00,
0x3d490000,0x3effbf00,0x3ec6beb5,0x3ea2beb5,0x3e15bdc8,0x3ef5befb,0x3ee2bed5,0x3e71be8e,0x3e71be44,0x3ee2beed,0x3ef5beed,0x3e15be44,0x3ea2be8e,0x3ec6bed5,0x3effbefb,0x3d49bdc8,
0x3efbbf00,0xbdc80000,0xbdc80000,0xbefb3f00,0x3ed5beed,0xbe8e3e44,0xbe8e3e44,0xbed53eed,0x3e8ebeb5,0xbed53eb5,0xbed53eb5,0xbe8e3eb5,0x3dc8be44,0xbefb3eed,0xbefb3eed,0xbdc83e44,
0xbe150000,0xbef53f00,0xbe713eb5,0x3ee2beb5,0xbec63e8e,0xbea23ed5,0x3d493dc8,0x3effbefb,0xbeff3eed,0xbd493e44,0x3ea2be44,0x3ec6beed,0xbee23efb,0x3e71bdc8,0x3ef5bed5,0x3e15be8e,
0xbeed3f00,0x3e440000,0x3eedbf00,0xbe440000,0xbe443eb5,0x3eedbeb5,0x3e44beb5,0xbeed3eb5,0x3e440000,0x3eedbf00,0xbe440000,0xbeed3f00,0x3eedbeb5,0x3e44beb5,0xbeed3eb5,0xbe443eb5,
0x3e710000,0x3ee2bf00,0xbef53eb5,0xbe153eb5,0x3effbed5,0x3d49be8e,0xbec63efb,0x3ea2bdc8,0x3ea2beed,0xbec63e44,0x3d493e44,0x3effbeed,0xbe15bdc8,0xbef53efb,0x3ee2be8e,0x3e71bed5,
0x3ed5bf00,0xbe8e0000,0x3e8e0000,0x3ed5bf00,0xbdc8be44,0xbefb3eed,0x3efbbeed,0xbdc8be44,0xbefb3eb5,0xbdc83eb5,0x3dc8beb5,0xbefb3eb5,0xbe8e3eed,0x3ed5be44,0xbed53e44,0xbe8e3eed,
0xbea20000,0xbec63f00,0x3d49beb5,0xbeff3eb5,0xbee23efb,0x3e713dc8,0xbef53e8e,0xbe153ed5,0x3e153e44,0x3ef5beed,0xbe713eed,0x3ee2be44,0x3effbed5,0xbd49be8e,0x3ec6bdc8,0x3ea2befb,
0xbeb53f00,0xbeb50000,0xbeb53f00,0xbeb50000,0x3eb50000,0xbeb53f00,0x3eb50000,0xbeb53f00,0x3eb5bf00,0x3eb50000,0x3eb5bf00,0x3eb50000,0xbeb50000,0x3eb5bf00,0xbeb50000,0x3eb5bf00,
0x3eff0000,0xbd49bf00,0x3ea2beb5,0xbec6beb5,0xbef53dc8,0x3e153efb,0xbe713ed5,0x3ee23e8e,0x3ee2be44,0xbe71beed,0x3e15beed,0xbef5be44,0xbec63e8e,0x3ea23ed5,0xbd493efb,0x3eff3dc8,
0xbdc8bf00,0xbefb0000,0xbefb0000,0x3dc83f00,0x3e8e3eed,0x3ed5be44,0x3ed5be44,0xbe8ebeed,0xbed5beb5,0xbe8e3eb5,0xbe8e3eb5,0x3ed53eb5,0x3efb3e44,0x3dc8beed,0x3dc8beed,0xbefbbe44,
0xbef50000,0x3e153f00,0x3ee23eb5,0x3e71beb5,0x3ea2be8e,0xbec6bed5,0xbeffbdc8,0x3d493efb,0xbd493eed,0x3eff3e44,0x3ec6be44,0xbea2beed,0xbe71befb,0xbee23dc8,0xbe153ed5,0x3ef53e8e,
0x3e443f00,0x3eed0000,0xbe44bf00,0xbeed0000,0xbeedbeb5,0xbe443eb5,0x3eed3eb5,0x3e44beb5,0x3eed0000,0xbe44bf00,0xbeed0000,0x3e443f00,0xbe443eb5,0x3eed3eb5,0x3e44beb5,0xbeedbeb5,
0x3ee20000,0xbe71bf00,0xbe153eb5,0x3ef53eb5,0xbd493ed5,0x3eff3e8e,0xbea2befb,0xbec63dc8,0xbec6beed,0xbea23e44,0x3eff3e44,0xbd49beed,0x3ef53dc8,0xbe15befb,0xbe713e8e,0x3ee23ed5,
0xbe8ebf00,0xbed50000,0x3ed50000,0xbe8ebf00,0x3efb3e44,0xbdc8beed,0x3dc83eed,0x3efb3e44,0xbdc83eb5,0x3efb3eb5,0xbefbbeb5,0xbdc83eb5,0xbed5beed,0xbe8e3e44,0x3e8ebe44,0xbed5beed,
0xbec60000,0x3ea23f00,0xbeffbeb5,0xbd493eb5,0xbe71befb,0xbee2bdc8,0x3e15be8e,0xbef5bed5,0x3ef53e44,0xbe15beed,0x3ee23eed,0x3e71be44,0x3d493ed5,0x3eff3e8e,0xbea23dc8,0x3ec63efb,
0x3f003f00,0xbf003f00,0x3f003f00,0xbf003f00,0x3f003f00,0xbf003f00,0x3f003f00,0xbf003f00,0x3f003f00,0xbf003f00,0x3f003f00,0xbf003f00,0x3f003f00,0xbf003f00,0x3f003f00,0xbf003f00,
0xbeffbf00,0x3d490000,0xbea2beb5,0x3ec63eb5,0xbef5befb,0x3e153dc8,0xbe71be8e,0x3ee23ed5,0xbee2beed,0x3e713e44,0xbe15be44,0x3ef53eed,0xbec6bed5,0x3ea23e8e,0xbd49bdc8,0x3eff3efb,
0x3efb3f00,0xbdc80000,0xbdc80000,0xbefbbf00,0x3ed53eed,0xbe8ebe44,0xbe8ebe44,0xbed5beed,0x3e8e3eb5,0xbed5beb5,0xbed5beb5,0xbe8ebeb5,0x3dc83e44,0xbefbbeed,0xbefbbeed,0xbdc8be44,
0xbef5bf00,0x3e150000,0x3ee23eb5,0x3e713eb5,0xbea2bed5,0x3ec63e8e,0x3eff3efb,0xbd493dc8,0xbd49be44,0x3eff3eed,0x3ec63eed,0xbea2be44,0x3e713dc8,0x3ee23efb,0x3e153e8e,0xbef5bed5,
0x3eed3f00,0xbe440000,0xbeedbf00,0x3e440000,0x3e443eb5,0xbeedbeb5,0xbe44beb5,0x3eed3eb5,0xbe440000,0xbeedbf00,0x3e440000,0x3eed3f00,0xbeedbeb5,0xbe44beb5,0x3eed3eb5,0x3e443eb5,
0xbee2bf00,0x3e710000,0x3e153eb5,0xbef5beb5,0xbd49be8e,0x3eff3ed5,0xbea2bdc8,0xbec6befb,0x3ec63e44,0x3ea23eed,0xbeffbeed,0x3d49be44,0x3ef53efb,0xbe153dc8,0xbe71bed5,0x3ee23e8e,
0x3ed53f00,0xbe8e0000,0x3e8e0000,0x3ed53f00,0xbdc83e44,0xbefbbeed,0x3efb3eed,0xbdc83e44,0xbefbbeb5,0xbdc8beb5,0x3dc83eb5,0xbefbbeb5,0xbe8ebeed,0x3ed53e44,0xbed5be44,0xbe8ebeed,
0xbec6bf00,0x3ea20000,0xbeffbeb5,0xbd49beb5,0x3e71bdc8,0x3ee23efb,0xbe15bed5,0x3ef53e8e,0x3ef53eed,0xbe153e44,0x3ee23e44,0x3e713eed,0xbd493e8e,0xbeffbed5,0x3ea23efb,0xbec6bdc8,
0x3f00,0xbf000000,0x3f00,0xbf000000,0xbf00,0x3f000000,0xbf00,0x3f000000,0x3f00,0xbf000000,0x3f00,0xbf000000,0xbf00,0x3f000000,0xbf00,0x3f000000,
0x3d49bf00,0x3eff0000,0x3ec6beb5,0x3ea23eb5,0xbe153efb,0xbef5bdc8,0xbee23e8e,0xbe71bed5,0x3e71beed,0x3ee23e44,0x3ef5be44,0x3e153eed,0xbea23ed5,0xbec6be8e,0xbeff3dc8,0xbd49befb,
0xbdc83f00,0xbefb0000,0xbefb0000,0x3dc8bf00,0x3e8ebeed,0x3ed53e44,0x3ed53e44,0xbe8e3eed,0xbed53eb5,0xbe8ebeb5,0xbe8ebeb5,0x3ed5beb5,0x3efbbe44,0x3dc83eed,0x3dc83eed,0xbefb3e44,
0x3e15bf00,0x3ef50000,0x3e713eb5,0xbee23eb5,0xbec63ed5,0xbea2be8e,0x3d49befb,0x3effbdc8,0x3effbe44,0x3d493eed,0xbea23eed,0xbec6be44,0xbee2bdc8,0x3e71befb,0x3ef5be8e,0x3e153ed5,
0xbe443f00,0xbeed0000,0x3e44bf00,0x3eed0000,0x3eedbeb5,0x3e443eb5,0xbeed3eb5,0xbe44beb5,0xbeed0000,0x3e44bf00,0x3eed0000,0xbe443f00,0x3e443eb5,0xbeed3eb5,0xbe44beb5,0x3eedbeb5,
0x3e71bf00,0x3ee20000,0xbef53eb5,0xbe15beb5,0xbeff3e8e,0xbd49bed5,0x3ec63dc8,0xbea23efb,0x3ea23e44,0xbec63eed,0x3d49beed,0x3effbe44,0x3e15befb,0x3ef5bdc8,0xbee23ed5,0xbe71be8e,
0xbe8e3f00,0xbed50000,0x3ed50000,0xbe8e3f00,0x3efbbe44,0xbdc83eed,0x3dc8beed,0x3efbbe44,0xbdc8beb5,0x3efbbeb5,0xbefb3eb5,0xbdc8beb5,0xbed53eed,0xbe8ebe44,0x3e8e3e44,0xbed53eed,
0x3ea2bf00,0x3ec60000,0xbd49beb5,0x3effbeb5,0xbee23dc8,0x3e71befb,0xbef53ed5,0xbe15be8e,0xbe153eed,0xbef53e44,0x3e713e44,0xbee23eed,0x3effbe8e,0xbd493ed5,0x3ec6befb,0x3ea23dc8,
0x3eb53f00,0xbeb50000,0x3eb53f00,0xbeb50000,0xbeb50000,0xbeb5bf00,0xbeb50000,0xbeb5bf00,0xbeb5bf00,0x3eb50000,0xbeb5bf00,0x3eb50000,0x3eb50000,0x3eb53f00,0x3eb50000,0x3eb53f00,
0x3effbf00,0xbd490000,0x3ea2beb5,0xbec63eb5,0x3ef5befb,0xbe153dc8,0x3e71be8e,0xbee23ed5,0x3ee2beed,0xbe713e44,0x3e15be44,0xbef53eed,0x3ec6bed5,0xbea23e8e,0x3d49bdc8,0xbeff3efb,
0xbefb3f00,0x3dc80000,0x3dc80000,0x3efbbf00,0xbed53eed,0x3e8ebe44,0x3e8ebe44,0x3ed5beed,0xbe8e3eb5,0x3ed5beb5,0x3ed5beb5,0x3e8ebeb5,0xbdc83e44,0x3efbbeed,0x3efbbeed,0x3dc8be44,
0x3ef5bf00,0xbe150000,0xbee23eb5,0xbe713eb5,0x3ea2bed5,0xbec63e8e,0xbeff3efb,0x3d493dc8,0x3d49be44,0xbeff3eed,0xbec63eed,0x3ea2be44,0xbe713dc8,0xbee23efb,0xbe153e8e,0x3ef5bed5,
0xbeed3f00,0x3e440000,0x3eedbf00,0xbe440000,0xbe443eb5,0x3eedbeb5,0x3e44beb5,0xbeed3eb5,0x3e440000,0x3eedbf00,0xbe440000,0xbeed3f00,0x3eedbeb5,0x3e44beb5,0xbeed3eb5,0xbe443eb5,
0x3ee2bf00,0xbe710000,0xbe153eb5,0x3ef5beb5,0x3d49be8e,0xbeff3ed5,0x3ea2bdc8,0x3ec6befb,0xbec63e44,0xbea23eed,0x3effbeed,0xbd49be44,0xbef53efb,0x3e153dc8,0x3e71bed5,0xbee23e8e,
0xbed53f00,0x3e8e0000,0xbe8e0000,0xbed53f00,0x3dc83e44,0x3efbbeed,0xbefb3eed,0x3dc83e44,0x3efbbeb5,0x3dc8beb5,0xbdc83eb5,0x3efbbeb5,0x3e8ebeed,0xbed53e44,0x3ed5be44,0x3e8ebeed,
0x3ec6bf00,0xbea20000,0x3effbeb5,0x3d49beb5,0xbe71bdc8,0xbee23efb,0x3e15bed5,0xbef53e8e,0xbef53eed,0x3e153e44,0xbee23e44,0xbe713eed,0x3d493e8e,0x3effbed5,0xbea23efb,0x3ec6bdc8,
0xbeb53f00,0xbeb50000,0xbeb53f00,0xbeb50000,0x3eb50000,0xbeb53f00,0x3eb50000,0xbeb53f00,0x3eb5bf00,0x3eb50000,0x3eb5bf00,0x3eb50000,0xbeb50000,0x3eb5bf00,0xbeb50000,0x3eb5bf00,
0xbd49bf00,0xbeff0000,0xbec6beb5,0xbea23eb5,0x3e153efb,0x3ef5bdc8,0x3ee23e8e,0x3e71bed5,0xbe71beed,0xbee23e44,0xbef5be44,0xbe153eed,0x3ea23ed5,0x3ec6be8e,0x3eff3dc8,0x3d49befb,
0x3dc83f00,0x3efb0000,0x3efb0000,0xbdc8bf00,0xbe8ebeed,0xbed53e44,0xbed53e44,0x3e8e3eed,0x3ed53eb5,0x3e8ebeb5,0x3e8ebeb5,0xbed5beb5,0xbefbbe44,0xbdc83eed,0xbdc83eed,0x3efb3e44,
0xbe15bf00,0xbef50000,0xbe713eb5,0x3ee23eb5,0x3ec63ed5,0x3ea2be8e,0xbd49befb,0xbeffbdc8,0xbeffbe44,0xbd493eed,0x3ea23eed,0x3ec6be44,0x3ee2bdc8,0xbe71befb,0xbef5be8e,0xbe153ed5,
0x3e443f00,0x3eed0000,0xbe44bf00,0xbeed0000,0xbeedbeb5,0xbe443eb5,0x3eed3eb5,0x3e44beb5,0x3eed0000,0xbe44bf00,0xbeed0000,0x3e443f00,0xbe443eb5,0x3eed3eb5,0x3e44beb5,0xbeedbeb5,
0xbe71bf00,0xbee20000,0x3ef53eb5,0x3e15beb5,0x3eff3e8e,0x3d49bed5,0xbec63dc8,0x3ea23efb,0xbea23e44,0x3ec63eed,0xbd49beed,0xbeffbe44,0xbe15befb,0xbef5bdc8,0x3ee23ed5,0x3e71be8e,
0x3e8e3f00,0x3ed50000,0xbed50000,0x3e8e3f00,0xbefbbe44,0x3dc83eed,0xbdc8beed,0xbefbbe44,0x3dc8beb5,0xbefbbeb5,0x3efb3eb5,0x3dc8beb5,0x3ed53eed,0x3e8ebe44,0xbe8e3e44,0x3ed53eed,
0xbea2bf00,0xbec60000,0x3d49beb5,0xbeffbeb5,0x3ee23dc8,0xbe71befb,0x3ef53ed5,0x3e15be8e,0x3e153eed,0x3ef53e44,0xbe713e44,0x3ee23eed,0xbeffbe8e,0x3d493ed5,0xbec6befb,0xbea23dc8,
0x3f003f00,0xbf003f00,0x3f003f00,0xbf003f00,0x3f003f00,0xbf003f00,0x3f003f00,0xbf003f00,0x3f003f00,0xbf003f00,0x3f003f00,0xbf003f00,0x3f003f00,0xbf003f00,0x3f003f00,0xbf003f00,
0x3d490000,0x3eff3f00,0x3ec63eb5,0x3ea23eb5,0x3e153dc8,0x3ef53efb,0x3ee23ed5,0x3e713e8e,0x3e713e44,0x3ee23eed,0x3ef53eed,0x3e153e44,0x3ea23e8e,0x3ec63ed5,0x3eff3efb,0x3d493dc8,
0xbefbbf00,0x3dc80000,0x3dc80000,0x3efb3f00,0xbed5beed,0x3e8e3e44,0x3e8e3e44,0x3ed53eed,0xbe8ebeb5,0x3ed53eb5,0x3ed53eb5,0x3e8e3eb5,0xbdc8be44,0x3efb3eed,0x3efb3eed,0x3dc83e44,
0xbe150000,0xbef5bf00,0xbe71beb5,0x3ee23eb5,0xbec6be8e,0xbea2bed5,0x3d49bdc8,0x3eff3efb,0xbeffbeed,0xbd49be44,0x3ea23e44,0x3ec63eed,0xbee2befb,0x3e713dc8,0x3ef53ed5,0x3e153e8e,
0x3eed3f00,0xbe440000,0xbeedbf00,0x3e440000,0x3e443eb5,0xbeedbeb5,0xbe44beb5,0x3eed3eb5,0xbe440000,0xbeedbf00,0x3e440000,0x3eed3f00,0xbeedbeb5,0xbe44beb5,0x3eed3eb5,0x3e443eb5,
0x3e710000,0x3ee23f00,0xbef5beb5,0xbe15beb5,0x3eff3ed5,0x3d493e8e,0xbec6befb,0x3ea23dc8,0x3ea23eed,0xbec6be44,0x3d49be44,0x3eff3eed,0xbe153dc8,0xbef5befb,0x3ee23e8e,0x3e713ed5,
0xbed5bf00,0x3e8e0000,0xbe8e0000,0xbed5bf00,0x3dc8be44,0x3efb3eed,0xbefbbeed,0x3dc8be44,0x3efb3eb5,0x3dc83eb5,0xbdc8beb5,0x3efb3eb5,0x3e8e3eed,0xbed5be44,0x3ed53e44,0x3e8e3eed,
0xbea20000,0xbec6bf00,0x3d493eb5,0xbeffbeb5,0xbee2befb,0x3e71bdc8,0xbef5be8e,0xbe15bed5,0x3e15be44,0x3ef53eed,0xbe71beed,0x3ee23e44,0x3eff3ed5,0xbd493e8e,0x3ec63dc8,0x3ea23efb,
0x3f00,0xbf000000,0x3f00,0xbf000000,0xbf00,0x3f000000,0xbf00,0x3f000000,0x3f00,0xbf000000,0x3f00,0xbf000000,0xbf00,0x3f000000,0xbf00,0x3f000000,
0x3eff0000,0xbd493f00,0x3ea23eb5,0xbec63eb5,0xbef5bdc8,0x3e15befb,0xbe71bed5,0x3ee2be8e,0x3ee23e44,0xbe713eed,0x3e153eed,0xbef53e44,0xbec6be8e,0x3ea2bed5,0xbd49befb,0x3effbdc8,
0x3dc8bf00,0x3efb0000,0x3efb0000,0xbdc83f00,0xbe8e3eed,0xbed5be44,0xbed5be44,0x3e8ebeed,0x3ed5beb5,0x3e8e3eb5,0x3e8e3eb5,0xbed53eb5,0xbefb3e44,0xbdc8beed,0xbdc8beed,0x3efbbe44,
0xbef50000,0x3e15bf00,0x3ee2beb5,0x3e713eb5,0x3ea23e8e,0xbec63ed5,0xbeff3dc8,0x3d49befb,0xbd49beed,0x3effbe44,0x3ec63e44,0xbea23eed,0xbe713efb,0xbee2bdc8,0xbe15bed5,0x3ef5be8e,
0xbe443f00,0xbeed0000,0x3e44bf00,0x3eed0000,0x3eedbeb5,0x3e443eb5,0xbeed3eb5,0xbe44beb5,0xbeed0000,0x3e44bf00,0x3eed0000,0xbe443f00,0x3e443eb5,0xbeed3eb5,0xbe44beb5,0x3eedbeb5,
0x3ee20000,0xbe713f00,0xbe15beb5,0x3ef5beb5,0xbd49bed5,0x3effbe8e,0xbea23efb,0xbec6bdc8,0xbec63eed,0xbea2be44,0x3effbe44,0xbd493eed,0x3ef5bdc8,0xbe153efb,0xbe71be8e,0x3ee2bed5,
0x3e8ebf00,0x3ed50000,0xbed50000,0x3e8ebf00,0xbefb3e44,0x3dc8beed,0xbdc83eed,0xbefb3e44,0x3dc83eb5,0xbefb3eb5,0x3efbbeb5,0x3dc83eb5,0x3ed5beed,0x3e8e3e44,0xbe8ebe44,0x3ed5beed,
0xbec60000,0x3ea2bf00,0xbeff3eb5,0xbd49beb5,0xbe713efb,0xbee23dc8,0x3e153e8e,0xbef53ed5,0x3ef5be44,0xbe153eed,0x3ee2beed,0x3e713e44,0x3d49bed5,0x3effbe8e,0xbea2bdc8,0x3ec6befb,
0x3eb53f00,0xbeb50000,0x3eb53f00,0xbeb50000,0xbeb50000,0xbeb5bf00,0xbeb50000,0xbeb5bf00,0xbeb5bf00,0x3eb50000,0xbeb5bf00,0x3eb50000,0x3eb50000,0x3eb53f00,0x3eb50000,0x3eb53f00,
0xbd490000,0xbeff3f00,0xbec63eb5,0xbea23eb5,0xbe153dc8,0xbef53efb,0xbee23ed5,0xbe713e8e,0xbe713e44,0xbee23eed,0xbef53eed,0xbe153e44,0xbea23e8e,0xbec63ed5,0xbeff3efb,0xbd493dc8,
0x3efbbf00,0xbdc80000,0xbdc80000,0xbefb3f00,0x3ed5beed,0xbe8e3e44,0xbe8e3e44,0xbed53eed,0x3e8ebeb5,0xbed53eb5,0xbed53eb5,0xbe8e3eb5,0x3dc8be44,0xbefb3eed,0xbefb3eed,0xbdc83e44,
0x3e150000,0x3ef5bf00,0x3e71beb5,0xbee23eb5,0x3ec6be8e,0x3ea2bed5,0xbd49bdc8,0xbeff3efb,0x3effbeed,0x3d49be44,0xbea23e44,0xbec63eed,0x3ee2befb,0xbe713dc8,0xbef53ed5,0xbe153e8e,
0xbeed3f00,0x3e440000,0x3eedbf00,0xbe440000,0xbe443eb5,0x3eedbeb5,0x3e44beb5,0xbeed3eb5,0x3e440000,0x3eedbf00,0xbe440000,0xbeed3f00,0x3eedbeb5,0x3e44beb5,0xbeed3eb5,0xbe443eb5,
0xbe710000,0xbee23f00,0x3ef5beb5,0x3e15beb5,0xbeff3ed5,0xbd493e8e,0x3ec6befb,0xbea23dc8,0xbea23eed,0x3ec6be44,0xbd49be44,0xbeff3eed,0x3e153dc8,0x3ef5befb,0xbee23e8e,0xbe713ed5,
0x3ed5bf00,0xbe8e0000,0x3e8e0000,0x3ed5bf00,0xbdc8be44,0xbefb3eed,0x3efbbeed,0xbdc8be44,0xbefb3eb5,0xbdc83eb5,0x3dc8beb5,0xbefb3eb5,0xbe8e3eed,0x3ed5be44,0xbed53e44,0xbe8e3eed,
0x3ea20000,0x3ec6bf00,0xbd493eb5,0x3effbeb5,0x3ee2befb,0xbe71bdc8,0x3ef5be8e,0x3e15bed5,0xbe15be44,0xbef53eed,0x3e71beed,0xbee23e44,0xbeff3ed5,0x3d493e8e,0xbec63dc8,0xbea23efb,
0xbeb53f00,0xbeb50000,0xbeb53f00,0xbeb50000,0x3eb50000,0xbeb53f00,0x3eb50000,0xbeb53f00,0x3eb5bf00,0x3eb50000,0x3eb5bf00,0x3eb50000,0xbeb50000,0x3eb5bf00,0xbeb50000,0x3eb5bf00,
0xbeff0000,0x3d493f00,0xbea23eb5,0x3ec63eb5,0x3ef5bdc8,0xbe15befb,0x3e71bed5,0xbee2be8e,0xbee23e44,0x3e713eed,0xbe153eed,0x3ef53e44,0x3ec6be8e,0xbea2bed5,0x3d49befb,0xbeffbdc8,
0xbdc8bf00,0xbefb0000,0xbefb0000,0x3dc83f00,0x3e8e3eed,0x3ed5be44,0x3ed5be44,0xbe8ebeed,0xbed5beb5,0xbe8e3eb5,0xbe8e3eb5,0x3ed53eb5,0x3efb3e44,0x3dc8beed,0x3dc8beed,0xbefbbe44,
0x3ef50000,0xbe15bf00,0xbee2beb5,0xbe713eb5,0xbea23e8e,0x3ec63ed5,0x3eff3dc8,0xbd49befb,0x3d49beed,0xbeffbe44,0xbec63e44,0x3ea23eed,0x3e713efb,0x3ee2bdc8,0x3e15bed5,0xbef5be8e,
0x3e443f00,0x3eed0000,0xbe44bf00,0xbeed0000,0xbeedbeb5,0xbe443eb5,0x3eed3eb5,0x3e44beb5,0x3eed0000,0xbe44bf00,0xbeed0000,0x3e443f00,0xbe443eb5,0x3eed3eb5,0x3e44beb5,0xbeedbeb5,
0xbee20000,0x3e713f00,0x3e15beb5,0xbef5beb5,0x3d49bed5,0xbeffbe8e,0x3ea23efb,0x3ec6bdc8,0x3ec63eed,0x3ea2be44,0xbeffbe44,0x3d493eed,0xbef5bdc8,0x3e153efb,0x3e71be8e,0xbee2bed5,
0xbe8ebf00,0xbed50000,0x3ed50000,0xbe8ebf00,0x3efb3e44,0xbdc8beed,0x3dc83eed,0x3efb3e44,0xbdc83eb5,0x3efb3eb5,0xbefbbeb5,0xbdc83eb5,0xbed5beed,0xbe8e3e44,0x3e8ebe44,0xbed5beed,
0x3ec60000,0xbea2bf00,0x3eff3eb5,0x3d49beb5,0x3e713efb,0x3ee23dc8,0xbe153e8e,0x3ef53ed5,0xbef5be44,0x3e153eed,0xbee2beed,0xbe713e44,0xbd49bed5,0xbeffbe8e,0x3ea2bdc8,0xbec6befb,
0x3f800000,0x0,0x3f800000,0x0,0x3f800000,0x0,0x3f800000,0x0,0x3f800000,0x0,0x3f800000,0x0,0x3f800000,0x0,0x3f800000,0x0,
0x3f800000,0x0,0x3f7fec43,0xbcc90ab0,0x3f7fb10f,0xbd48fb30,0x3f7f4e6d,0xbd96a905,0x3f7ec46d,0xbdc8bd36,0x3f7e1324,0xbdfab273,0x3f7d3aac,0xbe164083,0x3f7c3b28,0xbe2f10a2,
0x3f800000,0x0,0x3f7ffec4,0xbbc90f88,0x3f7ffb11,0xbc490e90,0x3f7ff4e6,0xbc96c9b6,0x3f7fec43,0xbcc90ab0,0x3f7fe129,0xbcfb49ba,0x3f7fd397,0xbd16c32c,0x3f7fc38f,0xbd2fe007,
0x3f800000,0x0,0x3f7fe129,0xbcfb49ba,0x3f7f84ab,0xbd7b2b74,0x3f7eea9d,0xbdbc3ac3,0x3f7e1324,0xbdfab273,0x3f7cfe73,0xbe1c76de,0x3f7baccd,0xbe3b6ecf,0x3f7a1e84,0xbe5a3997,
0x3f800000,0x0,0x3f7ffb11,0xbc490e90,0x3f7fec43,0xbcc90ab0,0x3f7fd397,0xbd16c32c,0x3f7fb10f,0xbd48fb30,0x3f7f84ab,0xbd7b2b74,0x3f7f4e6d,0xbd96a905,0x3f7f0e58,0xbdafb680,
0x3f800000,0x0,0x3f7fd397,0xbd16c32c,0x3f7f4e6d,0xbd96a905,0x3f7e70b0,0xbde1bc2e,0x3f7d3aac,0xbe164083,0x3f7baccd,0xbe3b6ecf,0x3f79c79d,0xbe605c13,0x3f778bc5,0xbe827dc0,
0x3f800000,0x0,0x3f7ff4e6,0xbc96c9b6,0x3f7fd397,0xbd16c32c,0x3f7f9c18,0xbd621469,0x3f7f4e6d,0xbd96a905,0x3f7eea9d,0xbdbc3ac3,0x3f7e70b0,0xbde1bc2e,0x3f7de0b1,0xbe039502,
0x3f800000,0x0,0x3f7fc38f,0xbd2fe007,0x3f7f0e58,0xbdafb680,0x3f7de0b1,0xbe039502,0x3f7c3b28,0xbe2f10a2,0x3f7a1e84,0xbe5a3997,0x3f778bc5,0xbe827dc0,0x3f748422,0xbe97a117,
0x3f800000,0x0,0x3f7fb10f,0xbd48fb30,0x3f7ec46d,0xbdc8bd36,0x3f7d3aac,0xbe164083,0x3f7b14be,0xbe47c5c2,0x3f7853f8,0xbe78cfcc,0x3f74fa0b,0xbe94a031,0x3f710908,0xbeac7cd4,
0x3f800000,0x0,0x3f7f4e6d,0xbd96a905,0x3f7d3aac,0xbe164083,0x3f79c79d,0xbe605c13,0x3f74fa0b,0xbe94a031,0x3f6ed89e,0xbeb8442a,0x3f676bd8,0xbedae880,0x3f5ebe05,0xbefc5d27,
0x3f800000,0x0,0x3f7f9c18,0xbd621469,0x3f7e70b0,0xbde1bc2e,0x3f7c7eb0,0xbe28defc,0x3f79c79d,0xbe605c13,0x3f764d97,0xbe8b9507,0x3f721352,0xbea68f12,0x3f6d1c1d,0xbec1071e,
0x3f800000,0x0,0x3f7f2f9d,0xbda3308c,0x3f7cbfc9,0xbe22abb6,0x3f78b47b,0xbe72b651,0x3f731447,0xbea09ae5,0x3f6be858,0xbec6d529,0x3f633c5a,0xbeebcbbb,0x3f591e6a,0xbf07a136,
0x3f800000,0x0,0x3f7f84ab,0xbd7b2b74,0x3f7e1324,0xbdfab273,0x3f7baccd,0xbe3b6ecf,0x3f7853f8,0xbe78cfcc,0x3f740bdd,0xbe9aa086,0x3f6ed89e,0xbeb8442a,0x3f68bf3c,0xbed53641,
0x3f800000,0x0,0x3f7f0e58,0xbdafb680,0x3f7c3b28,0xbe2f10a2,0x3f778bc5,0xbe827dc0,0x3f710908,0xbeac7cd4,0x3f68bf3c,0xbed53641,0x3f5ebe05,0xbefc5d27,0x3f531849,0xbf10d3cd,
0x3f800000,0x0,0x3f7f6ac7,0xbd8a200a,0x3f7dabcc,0xbe09cf86,0x3f7ac516,0xbe4dee60,0x3f76ba07,0xbe888e93,0x3f718f57,0xbea986c4,0x3f6b4b0c,0xbec9b953,0x3f63f473,0xbee900b7,
0x3f800000,0x0,0x3f7eea9d,0xbdbc3ac3,0x3f7baccd,0xbe3b6ecf,0x3f764d97,0xbe8b9507,0x3f6ed89e,0xbeb8442a,0x3f655e0b,0xbee363fa,0x3f59f26a,0xbf064b82,0x3f4cae79,0xbf19c200,
0x3f800000,0x0,0x3f7ec46d,0xbdc8bd36,0x3f7b14be,0xbe47c5c2,0x3f74fa0b,0xbe94a031,0x3f6c835e,0xbec3ef15,0x3f61c598,0xbef15aea,0x3f54db31,0xbf0e39da,0x3f45e403,0xbf226799,
0x3f800000,0x0,0x3f7e1324,0xbdfab273,0x3f7853f8,0xbe78cfcc,0x3f6ed89e,0xbeb8442a,0x3f61c598,0xbef15aea,0x3f514d3d,0xbf13682a,0x3f3daef9,0xbf2beb4a,0x3f273656,0xbf41d870,
0x3f800000,0x0,0x3f7e9bc9,0xbdd53db9,0x3f7a7302,0xbe541501,0x3f73913f,0xbe9d9e78,0x3f6a09a7,0xbecf7bca,0x3f5df6be,0xbeff17b2,0x3f4f7a1f,0xbf15f6d9,0x3f3ebc1b,0xbf2ac082,
0x3f800000,0x0,0x3f7de0b1,0xbe039502,0x3f778bc5,0xbe827dc0,0x3f6d1c1d,0xbec1071e,0x3f5ebe05,0xbefc5d27,0x3f4cae79,0xbf19c200,0x3f373a23,0xbf32c8c9,0x3f1ebc12,0xbf48d8b3,
0x3f800000,0x0,0x3f7e70b0,0xbde1bc2e,0x3f79c79d,0xbe605c13,0x3f721352,0xbea68f12,0x3f676bd8,0xbedae880,0x3f59f26a,0xbf064b82,0x3f49d112,0xbf1d7fd1,0x3f373a23,0xbf32c8c9,
0x3f800000,0x0,0x3f7dabcc,0xbe09cf86,0x3f76ba07,0xbe888e93,0x3f6b4b0c,0xbec9b953,0x3f5b941a,0xbf039c3d,0x3f47de65,0xbf1ff6cb,0x3f3085bb,0xbf396842,0x3f15f6d9,0xbf4f7a1f,
0x3f800000,0x0,0x3f7e4323,0xbdee3876,0x3f791298,0xbe6c9a7f,0x3f708066,0xbeaf713a,0x3f64aa59,0xbee63375,0x3f55b993,0xbf0cead0,0x3f43e200,0xbf24d225,0x3f2f61a5,0xbf3a7ca4,
0x3f800000,0x0,0x3f7d7474,0xbe1008b7,0x3f75dec6,0xbe8e9a22,0x3f696591,0xbed25a09,0x3f584853,0xbf08f59b,0x3f42de29,0xbf26050a,0x3f299415,0xbf3fc767,0x3f0cead0,0xbf55b993,
0x3f800000,0x0,0x3f7d3aac,0xbe164083,0x3f74fa0b,0xbe94a031,0x3f676bd8,0xbedae880,0x3f54db31,0xbf0e39da,0x3f3daef9,0xbf2beb4a,0x3f226799,0xbf45e403,0x3f039c3d,0xbf5b941a,
0x3f800000,0x0,0x3f7c3b28,0xbe2f10a2,0x3f710908,0xbeac7cd4,0x3f5ebe05,0xbefc5d27,0x3f45e403,0xbf226799,0x3f273656,0xbf41d870,0x3f039c3d,0xbf5b941a,0x3eb8442a,0xbf6ed89e,
0x3f800000,0x0,0x3f7cfe73,0xbe1c76de,0x3f740bdd,0xbe9aa086,0x3f655e0b,0xbee363fa,0x3f514d3d,0xbf13682a,0x3f385216,0xbf31a81d,0x3f1b02c6,0xbf4bbbf8,0x3ef41f07,0xbf6106f2,
0x3f800000,0x0,0x3f7bf531,0xbe354098,0x3f6ff573,0xbeb263ef,0x3f5c61c7,0xbf0242b1,0x3f41d870,0xbf273656,0x3f212ff9,0xbf46e22a,0x3ef6e0cb,0xbf604621,0x3ea395c5,0xbf7294f8,
0x3f800000,0x0,0x3f7cbfc9,0xbe22abb6,0x3f731447,0xbea09ae5,0x3f633c5a,0xbeebcbbb,0x3f4d9f02,0xbf187fc0,0x3f32c8c9,0xbf373a23,0x3f13682a,0xbf514d3d,0x3ee0924f,0xbf660f88,
0x3f800000,0x0,0x3f7baccd,0xbe3b6ecf,0x3f6ed89e,0xbeb8442a,0x3f59f26a,0xbf064b82,0x3f3daef9,0xbf2beb4a,0x3f1b02c6,0xbf4bbbf8,0x3ee63375,0xbf64aa59,0x3e8e9a22,0xbf75dec6,
0x3f800000,0x0,0x3f7c7eb0,0xbe28defc,0x3f721352,0xbea68f12,0x3f6106f2,0xbef41f07,0x3f49d112,0xbf1d7fd1,0x3f2d1469,0xbf3ca003,0x3f0b9a6b,0xbf5695e5,0x3ecc9b8b,0xbf6aab7b,
0x3f800000,0x0,0x3f7b61fc,0xbe419b37,0x3f6db293,0xbebe1d4a,0x3f577026,0xbf0a48ad,0x3f396842,0xbf3085bb,0x3f14b039,0xbf5064af,0x3ed53641,0xbf68bf3c,0x3e72b651,0xbf78b47b,
0x3f800000,0x0,0x3f800000,0x0,0x3f800000,0x0,0x3f800000,0x0,0x3f800000,0x0,0x3f800000,0x0,0x3f800000,0x0,0x3f800000,0x0,
0x3f7b14be,0xbe47c5c2,0x3f79c79d,0xbe605c13,0x3f7853f8,0xbe78cfcc,0x3f76ba07,0xbe888e93,0x3f74fa0b,0xbe94a031,0x3f731447,0xbea09ae5,0x3f710908,0xbeac7cd4,0x3f6ed89e,0xbeb8442a,
0x3f7fb10f,0xbd48fb30,0x3f7f9c18,0xbd621469,0x3f7f84ab,0xbd7b2b74,0x3f7f6ac7,0xbd8a200a,0x3f7f4e6d,0xbd96a905,0x3f7f2f9d,0xbda3308c,0x3f7f0e58,0xbdafb680,0x3f7eea9d,0xbdbc3ac3,
0x3f7853f8,0xbe78cfcc,0x3f764d97,0xbe8b9507,0x3f740bdd,0xbe9aa086,0x3f718f57,0xbea986c4,0x3f6ed89e,0xbeb8442a,0x3f6be858,0xbec6d529,0x3f68bf3c,0xbed53641,0x3f655e0b,0xbee363fa,
0x3f7ec46d,0xbdc8bd36,0x3f7e70b0,0xbde1bc2e,0x3f7e1324,0xbdfab273,0x3f7dabcc,0xbe09cf86,0x3f7d3aac,0xbe164083,0x3f7cbfc9,0xbe22abb6,0x3f7c3b28,0xbe2f10a2,0x3f7baccd,0xbe3b6ecf,
0x3f74fa0b,0xbe94a031,0x3f721352,0xbea68f12,0x3f6ed89e,0xbeb8442a,0x3f6b4b0c,0xbec9b953,0x3f676bd8,0xbedae880,0x3f633c5a,0xbeebcbbb,0x3f5ebe05,0xbefc5d27,0x3f59f26a,0xbf064b82,
0x3f7d3aac,0xbe164083,0x3f7c7eb0,0xbe28defc,0x3f7baccd,0xbe3b6ecf,0x3f7ac516,0xbe4dee60,0x3f79c79d,0xbe605c13,0x3f78b47b,0xbe72b651,0x3f778bc5,0xbe827dc0,0x3f764d97,0xbe8b9507,
0x3f710908,0xbeac7cd4,0x3f6d1c1d,0xbec1071e,0x3f68bf3c,0xbed53641,0x3f63f473,0xbee900b7,0x3f5ebe05,0xbefc5d27,0x3f591e6a,0xbf07a136,0x3f531849,0xbf10d3cd,0x3f4cae79,0xbf19c200,
0x3f6c835e,0xbec3ef15,0x3f676bd8,0xbedae880,0x3f61c598,0xbef15aea,0x3f5b941a,0xbf039c3d,0x3f54db31,0xbf0e39da,0x3f4d9f02,0xbf187fc0,0x3f45e403,0xbf226799,0x3f3daef9,0xbf2beb4a,
0x3f54db31,0xbf0e39da,0x3f49d112,0xbf1d7fd1,0x3f3daef9,0xbf2beb4a,0x3f3085bb,0xbf396842,0x3f226799,0xbf45e403,0x3f13682a,0xbf514d3d,0x3f039c3d,0xbf5b941a,0x3ee63375,0xbf64aa59,
0x3f676bd8,0xbedae880,0x3f6106f2,0xbef41f07,0x3f59f26a,0xbf064b82,0x3f5233c6,0xbf121eb0,0x3f49d112,0xbf1d7fd1,0x3f40d0da,0xbf286605,0x3f373a23,0xbf32c8c9,0x3f2d1469,0xbf3ca003,
0x3f4d9f02,0xbf187fc0,0x3f40d0da,0xbf286605,0x3f32c8c9,0xbf373a23,0x3f239da9,0xbf44e3f5,0x3f13682a,0xbf514d3d,0x3f0242b1,0xbf5c61c7,0x3ee0924f,0xbf660f88,0x3ebb31a0,0xbf6e46be,
0x3f61c598,0xbef15aea,0x3f59f26a,0xbf064b82,0x3f514d3d,0xbf13682a,0x3f47de65,0xbf1ff6cb,0x3f3daef9,0xbf2beb4a,0x3f32c8c9,0xbf373a23,0x3f273656,0xbf41d870,0x3f1b02c6,0xbf4bbbf8,
0x3f45e403,0xbf226799,0x3f373a23,0xbf32c8c9,0x3f273656,0xbf41d870,0x3f15f6d9,0xbf4f7a1f,0x3f039c3d,0xbf5b941a,0x3ee0924f,0xbf660f88,0x3eb8442a,0xbf6ed89e,0x3e8e9a22,0xbf75dec6,
0x3f5b941a,0xbf039c3d,0x3f5233c6,0xbf121eb0,0x3f47de65,0xbf1ff6cb,0x3f3ca003,0xbf2d1469,0x3f3085bb,0xbf396842,0x3f239da9,0xbf44e3f5,0x3f15f6d9,0xbf4f7a1f,0x3f07a136,0xbf591e6a,
0x3f3daef9,0xbf2beb4a,0x3f2d1469,0xbf3ca003,0x3f1b02c6,0xbf4bbbf8,0x3f07a136,0xbf591e6a,0x3ee63375,0xbf64aa59,0x3ebb31a0,0xbf6e46be,0x3e8e9a22,0xbf75dec6,0x3e419b37,0xbf7b61fc,
0x3f3504f3,0xbf3504f3,0x3f226799,0xbf45e403,0x3f0e39da,0xbf54db31,0x3ef15aea,0xbf61c598,0x3ec3ef15,0xbf6c835e,0x3e94a031,0xbf74fa0b,0x3e47c5c2,0xbf7b14be,0x3dc8bd36,0xbf7ec46d,
0x3f0e39da,0xbf54db31,0x3ee63375,0xbf64aa59,0x3eac7cd4,0xbf710908,0x3e605c13,0xbf79c79d,0x3dc8bd36,0xbf7ec46d,0xbcc90ab0,0xbf7fec43,0xbe164083,0xbf7d3aac,0xbe888e93,0xbf76ba07,
0x3f2beb4a,0xbf3daef9,0x3f173c07,0xbf4e8d90,0x3f00e7e4,0xbf5d2d53,0x3ed25a09,0xbf696591,0x3ea09ae5,0xbf731447,0x3e5a3997,0xbf7a1e84,0x3de1bc2e,0xbf7e70b0,0x3bc90f88,0xbf7ffec4,
0x3f039c3d,0xbf5b941a,0x3ecc9b8b,0xbf6aab7b,0x3e8e9a22,0xbf75dec6,0x3e1c76de,0xbf7cfe73,0x3cc90ab0,0xbf7fec43,0xbdd53db9,0xbf7e9bc9,0xbe6c9a7f,0xbf791298,0xbeb554ec,0xbf6f6830,
0x3f226799,0xbf45e403,0x3f0b9a6b,0xbf5695e5,0x3ee63375,0xbf64aa59,0x3eb263ef,0xbf6ff573,0x3e78cfcc,0xbf7853f8,0x3e09cf86,0xbf7dabcc,0x3cc90ab0,0xbf7fec43,0xbdafb680,0xbf7f0e58,
0x3ef15aea,0xbf61c598,0x3eb263ef,0xbf6ff573,0x3e605c13,0xbf79c79d,0x3dafb680,0xbf7f0e58,0xbd48fb30,0xbf7fb10f,0xbe3b6ecf,0xbf7baccd,0xbea09ae5,0xbf731447,0xbee0924f,0xbf660f88,
0x3f187fc0,0xbf4d9f02,0x3eff17b2,0xbf5df6be,0x3ec9b953,0xbf6b4b0c,0x3e919ddd,0xbf756d97,0x3e2f10a2,0xbf7c3b28,0x3d621469,0xbf7f9c18,0xbd7b2b74,0xbf7f84ab,0xbe354098,0xbf7bf531,
0x3edae880,0xbf676bd8,0x3e97a117,0xbf748422,0x3e22abb6,0xbf7cbfc9,0x3c96c9b6,0xbf7ff4e6,0xbdfab273,0xbf7e1324,0xbe8586ce,0xbf772417,0xbec9b953,0xbf6b4b0c,0xbf04f484,0xbf5ac450,
0x3ec3ef15,0xbf6c835e,0x3e78cfcc,0xbf7853f8,0x3dc8bd36,0xbf7ec46d,0xbd48fb30,0xbf7fb10f,0xbe47c5c2,0xbf7b14be,0xbeac7cd4,0xbf710908,0xbef15aea,0xbf61c598,0xbf187fc0,0xbf4d9f02,
0x3e47c5c2,0xbf7b14be,0x3cc90ab0,0xbf7fec43,0xbe164083,0xbf7d3aac,0xbea09ae5,0xbf731447,0xbef15aea,0xbf61c598,0xbf1d7fd1,0xbf49d112,0xbf3daef9,0xbf2beb4a,0xbf584853,0xbf08f59b,
0x3eac7cd4,0xbf710908,0x3e419b37,0xbf7b61fc,0x3d16c32c,0xbf7fd397,0xbdee3876,0xbf7e4323,0xbe888e93,0xbf76ba07,0xbed25a09,0xbf696591,0xbf0b9a6b,0xbf5695e5,0xbf2ac082,0xbf3ebc1b,
0x3e164083,0xbf7d3aac,0xbcfb49ba,0xbf7fe129,0xbe541501,0xbf7a7302,0xbec1071e,0xbf6d1c1d,0xbf08f59b,0xbf584853,0xbf2d1469,0xbf3ca003,0xbf4bbbf8,0xbf1b02c6,0xbf63f473,0xbee900b7,
0x3e94a031,0xbf74fa0b,0x3e09cf86,0xbf7dabcc,0xbcc90ab0,0xbf7fec43,0xbe3b6ecf,0xbf7baccd,0xbeac7cd4,0xbf710908,0xbef6e0cb,0xbf604621,0xbf1d7fd1,0xbf49d112,0xbf3b8f3b,0xbf2e3bde,
0x3dc8bd36,0xbf7ec46d,0xbdafb680,0xbf7f0e58,0xbe888e93,0xbf76ba07,0xbee0924f,0xbf660f88,0xbf187fc0,0xbf4d9f02,0xbf3b8f3b,0xbf2e3bde,0xbf584853,0xbf08f59b,0xbf6db293,0xbebe1d4a,
0x3e78cfcc,0xbf7853f8,0x3da3308c,0xbf7f2f9d,0xbdafb680,0xbf7f0e58,0xbe7ee6e1,0xbf77f110,0xbecf7bca,0xbf6a09a7,0xbf0cead0,0xbf55b993,0xbf2e3bde,0xbf3b8f3b,0xbf4ac77f,0xbf1c420c,
0x3d48fb30,0xbf7fb10f,0xbe1008b7,0xbf7d7474,0xbea68f12,0xbf721352,0xbeff17b2,0xbf5df6be,0xbf273656,0xbf41d870,0xbf48d8b3,0xbf1ebc12,0xbf633c5a,0xbeebcbbb,0xbf756d97,0xbe919ddd,
0x3f800000,0x0,0x3f800000,0x0,0x3f800000,0x0,0x3f800000,0x0,0x3f800000,0x0,0x3f800000,0x0,0x3f800000,0x0,0x3f800000,0x0,
0x3f6c835e,0xbec3ef15,0x3f6a09a7,0xbecf7bca,0x3f676bd8,0xbedae880,0x3f64aa59,0xbee63375,0x3f61c598,0xbef15aea,0x3f5ebe05,0xbefc5d27,0x3f5b941a,0xbf039c3d,0x3f584853,0xbf08f59b,
0x3f7ec46d,0xbdc8bd36,0x3f7e9bc9,0xbdd53db9,0x3f7e70b0,0xbde1bc2e,0x3f7e4323,0xbdee3876,0x3f7e1324,0xbdfab273,0x3f7de0b1,0xbe039502,0x3f7dabcc,0xbe09cf86,0x3f7d7474,0xbe1008b7,
0x3f61c598,0xbef15aea,0x3f5df6be,0xbeff17b2,0x3f59f26a,0xbf064b82,0x3f55b993,0xbf0cead0,0x3f514d3d,0xbf13682a,0x3f4cae79,0xbf19c200,0x3f47de65,0xbf1ff6cb,0x3f42de29,0xbf26050a,
0x3f7b14be,0xbe47c5c2,0x3f7a7302,0xbe541501,0x3f79c79d,0xbe605c13,0x3f791298,0xbe6c9a7f,0x3f7853f8,0xbe78cfcc,0x3f778bc5,0xbe827dc0,0x3f76ba07,0xbe888e93,0x3f75dec6,0xbe8e9a22,
0x3f54db31,0xbf0e39da,0x3f4f7a1f,0xbf15f6d9,0x3f49d112,0xbf1d7fd1,0x3f43e200,0xbf24d225,0x3f3daef9,0xbf2beb4a,0x3f373a23,0xbf32c8c9,0x3f3085bb,0xbf396842,0x3f299415,0xbf3fc767,
0x3f74fa0b,0xbe94a031,0x3f73913f,0xbe9d9e78,0x3f721352,0xbea68f12,0x3f708066,0xbeaf713a,0x3f6ed89e,0xbeb8442a,0x3f6d1c1d,0xbec1071e,0x3f6b4b0c,0xbec9b953,0x3f696591,0xbed25a09,
0x3f45e403,0xbf226799,0x3f3ebc1b,0xbf2ac082,0x3f373a23,0xbf32c8c9,0x3f2f61a5,0xbf3a7ca4,0x3f273656,0xbf41d870,0x3f1ebc12,0xbf48d8b3,0x3f15f6d9,0xbf4f7a1f,0x3f0cead0,0xbf55b993,
0x3f3504f3,0xbf3504f3,0x3f2beb4a,0xbf3daef9,0x3f226799,0xbf45e403,0x3f187fc0,0xbf4d9f02,0x3f0e39da,0xbf54db31,0x3f039c3d,0xbf5b941a,0x3ef15aea,0xbf61c598,0x3edae880,0xbf676bd8,
0x3ec3ef15,0xbf6c835e,0x3ea09ae5,0xbf731447,0x3e78cfcc,0xbf7853f8,0x3e2f10a2,0xbf7c3b28,0x3dc8bd36,0xbf7ec46d,0x3cc90ab0,0xbf7fec43,0xbd48fb30,0xbf7fb10f,0xbdfab273,0xbf7e1324,
0x3f226799,0xbf45e403,0x3f173c07,0xbf4e8d90,0x3f0b9a6b,0xbf5695e5,0x3eff17b2,0xbf5df6be,0x3ee63375,0xbf64aa59,0x3ecc9b8b,0xbf6aab7b,0x3eb263ef,0xbf6ff573,0x3e97a117,0xbf748422,
0x3e94a031,0xbf74fa0b,0x3e5a3997,0xbf7a1e84,0x3e09cf86,0xbf7dabcc,0x3d621469,0xbf7f9c18,0xbcc90ab0,0xbf7fec43,0xbdd53db9,0xbf7e9bc9,0xbe3b6ecf,0xbf7baccd,0xbe8586ce,0xbf772417,
0x3f0e39da,0xbf54db31,0x3f00e7e4,0xbf5d2d53,0x3ee63375,0xbf64aa59,0x3ec9b953,0xbf6b4b0c,0x3eac7cd4,0xbf710908,0x3e8e9a22,0xbf75dec6,0x3e605c13,0xbf79c79d,0x3e22abb6,0xbf7cbfc9,
0x3e47c5c2,0xbf7b14be,0x3de1bc2e,0xbf7e70b0,0x3cc90ab0,0xbf7fec43,0xbd7b2b74,0xbf7f84ab,0xbe164083,0xbf7d3aac,0xbe6c9a7f,0xbf791298,0xbea09ae5,0xbf731447,0xbec9b953,0xbf6b4b0c,
0x3ef15aea,0xbf61c598,0x3ed25a09,0xbf696591,0x3eb263ef,0xbf6ff573,0x3e919ddd,0xbf756d97,0x3e605c13,0xbf79c79d,0x3e1c76de,0xbf7cfe73,0x3dafb680,0xbf7f0e58,0x3c96c9b6,0xbf7ff4e6,
0x3dc8bd36,0xbf7ec46d,0x3bc90f88,0xbf7ffec4,0xbdafb680,0xbf7f0e58,0xbe354098,0xbf7bf531,0xbe888e93,0xbf76ba07,0xbeb554ec,0xbf6f6830,0xbee0924f,0xbf660f88,0xbf04f484,0xbf5ac450,
0x0,0xbf800000,0xbdc8bd36,0xbf7ec46d,0xbe47c5c2,0xbf7b14be,0xbe94a031,0xbf74fa0b,0xbec3ef15,0xbf6c835e,0xbef15aea,0xbf61c598,0xbf0e39da,0xbf54db31,0xbf226799,0xbf45e403,
0xbec3ef15,0xbf6c835e,0xbefc5d27,0xbf5ebe05,0xbf187fc0,0xbf4d9f02,0xbf3085bb,0xbf396842,0xbf45e403,0xbf226799,0xbf584853,0xbf08f59b,0xbf676bd8,0xbedae880,0xbf731447,0xbea09ae5,
0xbdc8bd36,0xbf7ec46d,0xbe4dee60,0xbf7ac516,0xbe9aa086,0xbf740bdd,0xbecc9b8b,0xbf6aab7b,0xbefc5d27,0xbf5ebe05,0xbf14b039,0xbf5064af,0xbf299415,0xbf3fc767,0xbf3ca003,0xbf2d1469,
0xbef15aea,0xbf61c598,0xbf14b039,0xbf5064af,0xbf2e3bde,0xbf3b8f3b,0xbf44e3f5,0xbf239da9,0xbf584853,0xbf08f59b,0xbf6816a8,0xbed8106b,0xbf740bdd,0xbe9aa086,0xbf7bf531,0xbe354098,
0xbe47c5c2,0xbf7b14be,0xbe9aa086,0xbf740bdd,0xbecf7bca,0xbf6a09a7,0xbf00e7e4,0xbf5d2d53,0xbf187fc0,0xbf4d9f02,0xbf2e3bde,0xbf3b8f3b,0xbf41d870,0xbf273656,0xbf531849,0xbf10d3cd,
0xbf0e39da,0xbf54db31,0xbf299415,0xbf3fc767,0xbf41d870,0xbf273656,0xbf5695e5,0xbf0b9a6b,0xbf676bd8,0xbedae880,0xbf740bdd,0xbe9aa086,0xbf7c3b28,0xbe2f10a2,0xbf7fd397,0xbd16c32c,
0xbe94a031,0xbf74fa0b,0xbecc9b8b,0xbf6aab7b,0xbf00e7e4,0xbf5d2d53,0xbf19c200,0xbf4cae79,0xbf3085bb,0xbf396842,0xbf44e3f5,0xbf239da9,0xbf5695e5,0xbf0b9a6b,0xbf655e0b,0xbee363fa,
0xbf226799,0xbf45e403,0xbf3ca003,0xbf2d1469,0xbf531849,0xbf10d3cd,0xbf655e0b,0xbee363fa,0xbf731447,0xbea09ae5,0xbf7bf531,0xbe354098,0xbf7fd397,0xbd16c32c,0xbf7e9bc9,0x3dd53db9,
0xbf3504f3,0xbf3504f3,0xbf4d9f02,0xbf187fc0,0xbf61c598,0xbef15aea,0xbf710908,0xbeac7cd4,0xbf7b14be,0xbe47c5c2,0xbf7fb10f,0xbd48fb30,0xbf7ec46d,0x3dc8bd36,0xbf7853f8,0x3e78cfcc,
0xbf6c835e,0xbec3ef15,0xbf79c79d,0xbe605c13,0xbf7fb10f,0xbd48fb30,0xbf7e1324,0x3dfab273,0xbf74fa0b,0x3e94a031,0xbf64aa59,0x3ee63375,0xbf4d9f02,0x3f187fc0,0xbf3085bb,0x3f396842,
0xbf45e403,0xbf226799,0xbf5c61c7,0xbf0242b1,0xbf6db293,0xbebe1d4a,0xbf796e4e,0xbe667c66,0xbf7f4e6d,0xbd96a905,0xbf7f2f9d,0x3da3308c,0xbf791298,0x3e6c9a7f,0xbf6d1c1d,0x3ec1071e,
0xbf74fa0b,0xbe94a031,0xbf7e4323,0xbdee3876,0xbf7f84ab,0x3d7b2b74,0xbf78b47b,0x3e72b651,0xbf6a09a7,0x3ecf7bca,0xbf53fac3,0x3f0f8784,0xbf373a23,0x3f32c8c9,0xbf14b039,0x3f5064af,
0xbf54db31,0xbf0e39da,0xbf68bf3c,0xbed53641,0xbf76ba07,0xbe888e93,0xbf7e70b0,0xbde1bc2e,0xbf7fb10f,0x3d48fb30,0xbf7a7302,0x3e541501,0xbf6ed89e,0x3eb8442a,0xbf5d2d53,0x3f00e7e4,
0xbf7b14be,0xbe47c5c2,0xbf7ffb11,0xbc490e90,0xbf7c3b28,0x3e2f10a2,0xbf6ff573,0x3eb263ef,0xbf5b941a,0x3f039c3d,0xbf3fc767,0x3f299415,0xbf1d7fd1,0x3f49d112,0xbeebcbbb,0x3f633c5a,
0xbf61c598,0xbef15aea,0xbf7294f8,0xbea395c5,0xbf7cbfc9,0xbe22abb6,0xbf7ffec4,0x3bc90f88,0xbf7c3b28,0x3e2f10a2,0xbf718f57,0x3ea986c4,0xbf604621,0x3ef6e0cb,0xbf48d8b3,0x3f1ebc12,
0xbf7ec46d,0xbdc8bd36,0xbf7eea9d,0x3dbc3ac3,0xbf75dec6,0x3e8e9a22,0xbf63f473,0x3ee900b7,0xbf49d112,0x3f1d7fd1,0xbf286605,0x3f40d0da,0xbf00e7e4,0x3f5d2d53,0xbea986c4,0x3f718f57,
0x3f800000,0x0,0x3f800000,0x0,0x3f800000,0x0,0x3f800000,0x0,0x3f800000,0x0,0x3f800000,0x0,0x3f800000,0x0,0x3f800000,0x0,
0x3f54db31,0xbf0e39da,0x3f514d3d,0xbf13682a,0x3f4d9f02,0xbf187fc0,0x3f49d112,0xbf1d7fd1,0x3f45e403,0xbf226799,0x3f41d870,0xbf273656,0x3f3daef9,0xbf2beb4a,0x3f396842,0xbf3085bb,
0x3f7d3aac,0xbe164083,0x3f7cfe73,0xbe1c76de,0x3f7cbfc9,0xbe22abb6,0x3f7c7eb0,0xbe28defc,0x3f7c3b28,0xbe2f10a2,0x3f7bf531,0xbe354098,0x3f7baccd,0xbe3b6ecf,0x3f7b61fc,0xbe419b37,
0x3f3daef9,0xbf2beb4a,0x3f385216,0xbf31a81d,0x3f32c8c9,0xbf373a23,0x3f2d1469,0xbf3ca003,0x3f273656,0xbf41d870,0x3f212ff9,0xbf46e22a,0x3f1b02c6,0xbf4bbbf8,0x3f14b039,0xbf5064af,
0x3f74fa0b,0xbe94a031,0x3f740bdd,0xbe9aa086,0x3f731447,0xbea09ae5,0x3f721352,0xbea68f12,0x3f710908,0xbeac7cd4,0x3f6ff573,0xbeb263ef,0x3f6ed89e,0xbeb8442a,0x3f6db293,0xbebe1d4a,
0x3f226799,0xbf45e403,0x3f1b02c6,0xbf4bbbf8,0x3f13682a,0xbf514d3d,0x3f0b9a6b,0xbf5695e5,0x3f039c3d,0xbf5b941a,0x3ef6e0cb,0xbf604621,0x3ee63375,0xbf64aa59,0x3ed53641,0xbf68bf3c,
0x3f676bd8,0xbedae880,0x3f655e0b,0xbee363fa,0x3f633c5a,0xbeebcbbb,0x3f6106f2,0xbef41f07,0x3f5ebe05,0xbefc5d27,0x3f5c61c7,0xbf0242b1,0x3f59f26a,0xbf064b82,0x3f577026,0xbf0a48ad,
0x3f039c3d,0xbf5b941a,0x3ef41f07,0xbf6106f2,0x3ee0924f,0xbf660f88,0x3ecc9b8b,0xbf6aab7b,0x3eb8442a,0xbf6ed89e,0x3ea395c5,0xbf7294f8,0x3e8e9a22,0xbf75dec6,0x3e72b651,0xbf78b47b,
0x3ec3ef15,0xbf6c835e,0x3eac7cd4,0xbf710908,0x3e94a031,0xbf74fa0b,0x3e78cfcc,0xbf7853f8,0x3e47c5c2,0xbf7b14be,0x3e164083,0xbf7d3aac,0x3dc8bd36,0xbf7ec46d,0x3d48fb30,0xbf7fb10f,
0xbe47c5c2,0xbf7b14be,0xbe888e93,0xbf76ba07,0xbeac7cd4,0xbf710908,0xbecf7bca,0xbf6a09a7,0xbef15aea,0xbf61c598,0xbf08f59b,0xbf584853,0xbf187fc0,0xbf4d9f02,0xbf273656,0xbf41d870,
0x3e78cfcc,0xbf7853f8,0x3e419b37,0xbf7b61fc,0x3e09cf86,0xbf7dabcc,0x3da3308c,0xbf7f2f9d,0x3cc90ab0,0xbf7fec43,0xbcfb49ba,0xbf7fe129,0xbdafb680,0xbf7f0e58,0xbe1008b7,0xbf7d7474,
0xbeac7cd4,0xbf710908,0xbed25a09,0xbf696591,0xbef6e0cb,0xbf604621,0xbf0cead0,0xbf55b993,0xbf1d7fd1,0xbf49d112,0xbf2d1469,0xbf3ca003,0xbf3b8f3b,0xbf2e3bde,0xbf48d8b3,0xbf1ebc12,
0x3dc8bd36,0xbf7ec46d,0x3d16c32c,0xbf7fd397,0xbcc90ab0,0xbf7fec43,0xbdafb680,0xbf7f0e58,0xbe164083,0xbf7d3aac,0xbe541501,0xbf7a7302,0xbe888e93,0xbf76ba07,0xbea68f12,0xbf721352,
0xbef15aea,0xbf61c598,0xbf0b9a6b,0xbf5695e5,0xbf1d7fd1,0xbf49d112,0xbf2e3bde,0xbf3b8f3b,0xbf3daef9,0xbf2beb4a,0xbf4bbbf8,0xbf1b02c6,0xbf584853,0xbf08f59b,0xbf633c5a,0xbeebcbbb,
0xbd48fb30,0xbf7fb10f,0xbdee3876,0xbf7e4323,0xbe3b6ecf,0xbf7baccd,0xbe7ee6e1,0xbf77f110,0xbea09ae5,0xbf731447,0xbec1071e,0xbf6d1c1d,0xbee0924f,0xbf660f88,0xbeff17b2,0xbf5df6be,
0xbf187fc0,0xbf4d9f02,0xbf2ac082,0xbf3ebc1b,0xbf3b8f3b,0xbf2e3bde,0xbf4ac77f,0xbf1c420c,0xbf584853,0xbf08f59b,0xbf63f473,0xbee900b7,0xbf6db293,0xbebe1d4a,0xbf756d97,0xbe919ddd,
0xbf3504f3,0xbf3504f3,0xbf45e403,0xbf226799,0xbf54db31,0xbf0e39da,0xbf61c598,0xbef15aea,0xbf6c835e,0xbec3ef15,0xbf74fa0b,0xbe94a031,0xbf7b14be,0xbe47c5c2,0xbf7ec46d,0xbdc8bd36,
0xbf7b14be,0xbe47c5c2,0xbf7f4e6d,0xbd96a905,0xbf7fb10f,0x3d48fb30,0xbf7c3b28,0x3e2f10a2,0xbf74fa0b,0x3e94a031,0xbf6a09a7,0x3ecf7bca,0xbf5b941a,0x3f039c3d,0xbf49d112,0x3f1d7fd1,
0xbf4d9f02,0xbf187fc0,0xbf5c61c7,0xbf0242b1,0xbf68bf3c,0xbed53641,0xbf7294f8,0xbea395c5,0xbf79c79d,0xbe605c13,0xbf7e4323,0xbdee3876,0xbf7ffb11,0xbc490e90,0xbf7eea9d,0x3dbc3ac3,
0xbf7fb10f,0xbd48fb30,0xbf7f2f9d,0x3da3308c,0xbf7a7302,0x3e541501,0xbf718f57,0x3ea986c4,0xbf64aa59,0x3ee63375,0xbf53fac3,0x3f0f8784,0xbf3fc767,0x3f299415,0xbf286605,0x3f40d0da,
0xbf61c598,0xbef15aea,0xbf6db293,0xbebe1d4a,0xbf76ba07,0xbe888e93,0xbf7cbfc9,0xbe22abb6,0xbf7fb10f,0xbd48fb30,0xbf7f84ab,0x3d7b2b74,0xbf7c3b28,0x3e2f10a2,0xbf75dec6,0x3e8e9a22,
0xbf7ec46d,0x3dc8bd36,0xbf791298,0x3e6c9a7f,0xbf6ed89e,0x3eb8442a,0xbf604621,0x3ef6e0cb,0xbf4d9f02,0x3f187fc0,0xbf373a23,0x3f32c8c9,0xbf1d7fd1,0x3f49d112,0xbf00e7e4,0x3f5d2d53,
0xbf710908,0xbeac7cd4,0xbf796e4e,0xbe667c66,0xbf7e70b0,0xbde1bc2e,0xbf7ffec4,0x3bc90f88,0xbf7e1324,0x3dfab273,0xbf78b47b,0x3e72b651,0xbf6ff573,0x3eb263ef,0xbf63f473,0x3ee900b7,
0xbf7853f8,0x3e78cfcc,0xbf6d1c1d,0x3ec1071e,0xbf5d2d53,0x3f00e7e4,0xbf48d8b3,0x3f1ebc12,0xbf3085bb,0x3f396842,0xbf14b039,0x3f5064af,0xbeebcbbb,0x3f633c5a,0xbea986c4,0x3f718f57,
0xbf6c835e,0x3ec3ef15,0xbf5b941a,0x3f039c3d,0xbf45e403,0x3f226799,0xbf2beb4a,0x3f3daef9,0xbf0e39da,0x3f54db31,0xbedae880,0x3f676bd8,0xbe94a031,0x3f74fa0b,0xbe164083,0x3f7d3aac,
0xbf0e39da,0x3f54db31,0xbecf7bca,0x3f6a09a7,0xbe78cfcc,0x3f7853f8,0xbd96a905,0x3f7f4e6d,0x3dc8bd36,0x3f7ec46d,0x3e888e93,0x3f76ba07,0x3edae880,0x3f676bd8,0x3f13682a,0x3f514d3d,
0xbf5b941a,0x3f039c3d,0xbf44e3f5,0x3f239da9,0xbf299415,0x3f3fc767,0xbf0a48ad,0x3f577026,0xbecf7bca,0x3f6a09a7,0xbe8586ce,0x3f772417,0xbde1bc2e,0x3f7e70b0,0x3d2fe007,0x3f7fc38f,
0xbedae880,0x3f676bd8,0xbe8586ce,0x3f772417,0xbdafb680,0x3f7f0e58,0x3dbc3ac3,0x3f7eea9d,0x3e888e93,0x3f76ba07,0x3eddbe79,0x3f66becc,0x3f15f6d9,0x3f4f7a1f,0x3f385216,0x3f31a81d,
0xbf45e403,0x3f226799,0xbf299415,0x3f3fc767,0xbf08f59b,0x3f584853,0xbec9b953,0x3f6b4b0c,0xbe78cfcc,0x3f7853f8,0xbdafb680,0x3f7f0e58,0x3d96a905,0x3f7f4e6d,0x3e6c9a7f,0x3f791298,
0xbe94a031,0x3f74fa0b,0xbde1bc2e,0x3f7e70b0,0x3d96a905,0x3f7f4e6d,0x3e827dc0,0x3f778bc5,0x3edae880,0x3f676bd8,0x3f15f6d9,0x3f4f7a1f,0x3f396842,0x3f3085bb,0x3f5695e5,0x3f0b9a6b,
0xbf2beb4a,0x3f3daef9,0xbf0a48ad,0x3f577026,0xbec9b953,0x3f6b4b0c,0xbe72b651,0x3f78b47b,0xbd96a905,0x3f7f4e6d,0x3dbc3ac3,0x3f7eea9d,0x3e827dc0,0x3f778bc5,0x3ed25a09,0x3f696591,
0xbe164083,0x3f7d3aac,0x3d2fe007,0x3f7fc38f,0x3e6c9a7f,0x3f791298,0x3ed25a09,0x3f696591,0x3f13682a,0x3f514d3d,0x3f385216,0x3f31a81d,0x3f5695e5,0x3f0b9a6b,0x3f6d1c1d,0x3ec1071e,
0x3e00,0x3e00,0x3e00,0x3e00,0x3e00,0x3e00,0x3e00,0x3e00,0x3e00,0x3e00,0x3e00,0x3e00,0x3e00,0x3e00,0x3e00,0x3e00,
0xbd443ded,0xbcc83dfb,0xbc493dff,0xbd153df5,0xbdb53db5,0xbdd53d8e,0xbdc63da2,0xbde23d71,0xbe000000,0xbdfbbcc8,0xbdffbc49,0xbdf5bd15,0xbdb5bdb5,0xbd8ebdd5,0xbda2bdc6,0xbd71bde2,
0xbdb53db5,0xbd443ded,0xbcc83dfb,0xbd8e3dd5,0xbe000000,0xbdedbd44,0xbdfbbcc8,0xbdd5bd8e,0xbe00,0x3d44bded,0x3cc8bdfb,0x3d8ebdd5,0x3e000000,0x3ded3d44,0x3dfb3cc8,0x3dd53d8e,
0xbded3d44,0xbd8e3dd5,0xbd153df5,0xbdc63da2,0xbdb5bdb5,0xbcc8bdfb,0xbd71bde2,0x3c49bdff,0x3e000000,0x3dd53d8e,0x3df53d15,0x3da23dc6,0xbdb53db5,0xbdfb3cc8,0xbde23d71,0xbdffbc49,
0xbe000000,0xbdb53db5,0xbd443ded,0xbded3d44,0xbe00,0x3db5bdb5,0x3d44bded,0x3dedbd44,0x3e00,0xbdb53db5,0xbd443ded,0xbded3d44,0xbe00,0x3db5bdb5,0x3d44bded,0x3dedbd44,
0xbdedbd44,0xbdd53d8e,0xbd713de2,0xbdff3c49,0x3db5bdb5,0x3dfb3cc8,0x3df5bd15,0x3dc63da2,0xbe000000,0xbd8ebdd5,0xbde2bd71,0xbc49bdff,0x3db53db5,0xbcc83dfb,0x3d153df5,0xbda23dc6,
0xbdb5bdb5,0xbded3d44,0xbd8e3dd5,0xbdfbbcc8,0x3e000000,0x3d443ded,0x3dd53d8e,0xbcc83dfb,0xbe00,0x3dedbd44,0x3d8ebdd5,0x3dfb3cc8,0xbe000000,0xbd44bded,0xbdd5bd8e,0x3cc8bdfb,
0xbd44bded,0xbdfb3cc8,0xbda23dc6,0xbde2bd71,0x3db53db5,0xbd8e3dd5,0x3c493dff,0xbdf53d15,0x3e000000,0x3cc83dfb,0x3dc63da2,0xbd713de2,0x3db5bdb5,0x3dd53d8e,0x3dffbc49,0x3d153df5,
0xbe00,0xbe000000,0xbdb53db5,0xbdb5bdb5,0x3e00,0xbe000000,0xbdb53db5,0xbdb5bdb5,0x3e00,0xbe000000,0xbdb53db5,0xbdb5bdb5,0x3e00,0xbe000000,0xbdb53db5,0xbdb5bdb5,
0x3d44bded,0xbdfbbcc8,0xbdc63da2,0xbd71bde2,0xbdb53db5,0xbd8ebdd5,0xbdffbc49,0x3d15bdf5,0xbe000000,0x3cc8bdfb,0xbda2bdc6,0x3de2bd71,0xbdb5bdb5,0x3dd5bd8e,0x3c49bdff,0x3df53d15,
0x3db5bdb5,0xbdedbd44,0xbdd53d8e,0xbcc8bdfb,0xbe000000,0x3d44bded,0xbd8ebdd5,0x3dfbbcc8,0xbe00,0x3ded3d44,0x3dd5bd8e,0x3cc83dfb,0x3e000000,0xbd443ded,0x3d8e3dd5,0xbdfb3cc8,
0x3dedbd44,0xbdd5bd8e,0xbde23d71,0x3c49bdff,0xbdb5bdb5,0x3dfbbcc8,0x3d15bdf5,0x3da23dc6,0x3e000000,0xbd8e3dd5,0x3d713de2,0xbdffbc49,0xbdb53db5,0xbcc8bdfb,0xbdf5bd15,0x3dc6bda2,
0x3e000000,0xbdb5bdb5,0xbded3d44,0x3d44bded,0xbe00,0x3db53db5,0x3dedbd44,0xbd443ded,0x3e00,0xbdb5bdb5,0xbded3d44,0x3d44bded,0xbe00,0x3db53db5,0x3dedbd44,0xbd443ded,
0x3ded3d44,0xbd8ebdd5,0xbdf53d15,0x3da2bdc6,0x3db5bdb5,0xbcc83dfb,0x3de23d71,0xbdff3c49,0xbe000000,0x3dd5bd8e,0xbd15bdf5,0x3dc63da2,0x3db53db5,0xbdfbbcc8,0xbd713de2,0xbc49bdff,
0x3db53db5,0xbd44bded,0xbdfb3cc8,0x3dd5bd8e,0x3e000000,0xbded3d44,0x3cc83dfb,0xbd8ebdd5,0xbe00,0x3d443ded,0x3dfbbcc8,0xbdd53d8e,0xbe000000,0x3dedbd44,0xbcc8bdfb,0x3d8e3dd5,
0x3d443ded,0xbcc8bdfb,0xbdff3c49,0x3df5bd15,0x3db53db5,0xbdd5bd8e,0xbda23dc6,0x3d71bde2,0x3e000000,0xbdfb3cc8,0x3c493dff,0xbd15bdf5,0x3db5bdb5,0xbd8e3dd5,0x3dc63da2,0xbde2bd71,
0x3e00,0xbe00,0xbe000000,0x3e000000,0x3e00,0xbe00,0xbe000000,0x3e000000,0x3e00,0xbe00,0xbe000000,0x3e000000,0x3e00,0xbe00,0xbe000000,0x3e000000,
0xbd443ded,0x3cc8bdfb,0xbdffbc49,0x3df53d15,0xbdb53db5,0x3dd5bd8e,0xbda2bdc6,0x3d713de2,0xbe000000,0x3dfb3cc8,0x3c49bdff,0xbd153df5,0xbdb5bdb5,0x3d8e3dd5,0x3dc6bda2,0xbde23d71,
0xbdb53db5,0x3d44bded,0xbdfbbcc8,0x3dd53d8e,0xbe000000,0x3ded3d44,0x3cc8bdfb,0xbd8e3dd5,0xbe00,0xbd443ded,0x3dfb3cc8,0xbdd5bd8e,0x3e000000,0xbdedbd44,0xbcc83dfb,0x3d8ebdd5,
0xbded3d44,0x3d8ebdd5,0xbdf5bd15,0x3da23dc6,0xbdb5bdb5,0x3cc83dfb,0x3de2bd71,0xbdffbc49,0x3e000000,0xbdd5bd8e,0xbd153df5,0x3dc6bda2,0xbdb53db5,0x3dfbbcc8,0xbd71bde2,0xbc493dff,
0xbe000000,0x3db5bdb5,0xbdedbd44,0x3d443ded,0xbe00,0xbdb53db5,0x3ded3d44,0xbd44bded,0x3e00,0x3db5bdb5,0xbdedbd44,0x3d443ded,0xbe00,0xbdb53db5,0x3ded3d44,0xbd44bded,
0xbdedbd44,0x3dd5bd8e,0xbde2bd71,0x3c493dff,0x3db5bdb5,0xbdfbbcc8,0x3d153df5,0x3da2bdc6,0xbe000000,0x3d8e3dd5,0x3d71bde2,0xbdff3c49,0x3db53db5,0x3cc8bdfb,0xbdf53d15,0x3dc63da2,
0xbdb5bdb5,0x3dedbd44,0xbdd5bd8e,0xbcc83dfb,0x3e000000,0xbd44bded,0xbd8e3dd5,0x3dfb3cc8,0xbe00,0xbded3d44,0x3dd53d8e,0x3cc8bdfb,0xbe000000,0x3d443ded,0x3d8ebdd5,0xbdfbbcc8,
0xbd44bded,0x3dfbbcc8,0xbdc6bda2,0xbd713de2,0x3db53db5,0x3d8ebdd5,0xbdff3c49,0x3d153df5,0x3e000000,0xbcc8bdfb,0xbda23dc6,0x3de23d71,0x3db5bdb5,0xbdd5bd8e,0x3c493dff,0x3df5bd15,
0xbe00,0x3e000000,0xbdb5bdb5,0xbdb53db5,0x3e00,0x3e000000,0xbdb5bdb5,0xbdb53db5,0x3e00,0x3e000000,0xbdb5bdb5,0xbdb53db5,0x3e00,0x3e000000,0xbdb5bdb5,0xbdb53db5,
0x3d44bded,0x3dfb3cc8,0xbda2bdc6,0xbde23d71,0xbdb53db5,0x3d8e3dd5,0x3c49bdff,0xbdf5bd15,0xbe000000,0xbcc83dfb,0x3dc6bda2,0xbd71bde2,0xbdb5bdb5,0xbdd53d8e,0x3dff3c49,0x3d15bdf5,
0x3db5bdb5,0x3ded3d44,0xbd8ebdd5,0xbdfb3cc8,0xbe000000,0xbd443ded,0x3dd5bd8e,0xbcc8bdfb,0xbe00,0xbdedbd44,0x3d8e3dd5,0x3dfbbcc8,0x3e000000,0x3d44bded,0xbdd53d8e,0x3cc83dfb,
0x3dedbd44,0x3dd53d8e,0xbd71bde2,0xbdffbc49,0xbdb5bdb5,0xbdfb3cc8,0x3df53d15,0x3dc6bda2,0x3e000000,0x3d8ebdd5,0xbde23d71,0xbc493dff,0xbdb53db5,0x3cc83dfb,0x3d15bdf5,0xbda2bdc6,
0x3e000000,0x3db53db5,0xbd44bded,0xbdedbd44,0xbe00,0xbdb5bdb5,0x3d443ded,0x3ded3d44,0x3e00,0x3db53db5,0xbd44bded,0xbdedbd44,0xbe00,0xbdb5bdb5,0x3d443ded,0x3ded3d44,
0x3ded3d44,0x3d8e3dd5,0xbd15bdf5,0xbdc6bda2,0x3db5bdb5,0x3cc8bdfb,0xbd713de2,0x3c493dff,0xbe000000,0xbdd53d8e,0x3df5bd15,0x3da2bdc6,0x3db53db5,0x3dfb3cc8,0xbde2bd71,0xbdff3c49,
0x3db53db5,0x3d443ded,0xbcc8bdfb,0xbd8ebdd5,0x3e000000,0x3dedbd44,0xbdfb3cc8,0xbdd53d8e,0xbe00,0xbd44bded,0x3cc83dfb,0x3d8e3dd5,0xbe000000,0xbded3d44,0x3dfbbcc8,0x3dd5bd8e,
0x3d443ded,0x3cc83dfb,0xbc49bdff,0xbd15bdf5,0x3db53db5,0x3dd53d8e,0xbdc6bda2,0xbde2bd71,0x3e000000,0x3dfbbcc8,0xbdff3c49,0xbdf53d15,0x3db5bdb5,0x3d8ebdd5,0xbda23dc6,0xbd713de2,
0x3d803d80,0x3e00,0x3e00,0x3e00,0x3e00,0x3e00,0x3e00,0x3e00,0x3e00,0x3e00,0x3e00,0x3e00,0x3e00,0x3e00,0x3e00,0x3e00,
0xbd803d80,0x3cc8bdfb,0x3c49bdff,0x3d15bdf5,0xbded3d44,0x3dd5bd8e,0x3dc6bda2,0x3de2bd71,0xbdedbd44,0x3dfb3cc8,0x3dff3c49,0x3df53d15,0xbd44bded,0x3d8e3dd5,0x3da23dc6,0x3d713de2,
0x3d803d80,0xbd443ded,0xbcc83dfb,0xbd8e3dd5,0xbdb5bdb5,0xbdedbd44,0xbdfbbcc8,0xbdd5bd8e,0x3db5bdb5,0x3d44bded,0x3cc8bdfb,0x3d8ebdd5,0x3db53db5,0x3ded3d44,0x3dfb3cc8,0x3dd53d8e,
0xbd803d80,0x3d8ebdd5,0x3d15bdf5,0x3dc6bda2,0x3d44bded,0x3cc83dfb,0x3d713de2,0xbc493dff,0x3d443ded,0xbdd5bd8e,0xbdf5bd15,0xbda2bdc6,0xbdedbd44,0x3dfbbcc8,0x3de2bd71,0x3dff3c49,
0x3d803d80,0xbdb53db5,0xbd443ded,0xbded3d44,0x3e000000,0x3db5bdb5,0x3d44bded,0x3dedbd44,0xbe000000,0xbdb53db5,0xbd443ded,0xbded3d44,0x3e000000,0x3db5bdb5,0x3d44bded,0x3dedbd44,
0xbd803d80,0x3dd5bd8e,0x3d71bde2,0x3dffbc49,0x3d443ded,0xbdfbbcc8,0xbdf53d15,0xbdc6bda2,0x3d44bded,0x3d8e3dd5,0x3de23d71,0x3c493dff,0xbded3d44,0x3cc8bdfb,0xbd15bdf5,0x3da2bdc6,
0x3d803d80,0xbded3d44,0xbd8e3dd5,0xbdfbbcc8,0xbdb53db5,0x3d443ded,0x3dd53d8e,0xbcc83dfb,0x3db53db5,0x3dedbd44,0x3d8ebdd5,0x3dfb3cc8,0x3db5bdb5,0xbd44bded,0xbdd5bd8e,0x3cc8bdfb,
0xbd803d80,0x3dfbbcc8,0x3da2bdc6,0x3de23d71,0xbdedbd44,0x3d8ebdd5,0xbc49bdff,0x3df5bd15,0xbded3d44,0xbcc8bdfb,0xbdc6bda2,0x3d71bde2,0xbd443ded,0xbdd5bd8e,0xbdff3c49,0xbd15bdf5,
0x3d803d80,0xbe000000,0xbdb53db5,0xbdb5bdb5,0xbe00,0xbe000000,0xbdb53db5,0xbdb5bdb5,0xbe00,0xbe000000,0xbdb53db5,0xbdb5bdb5,0xbe00,0xbe000000,0xbdb53db5,0xbdb5bdb5,
0xbd803d80,0x3dfb3cc8,0x3dc6bda2,0x3d713de2,0x3dedbd44,0x3d8e3dd5,0x3dff3c49,0xbd153df5,0x3ded3d44,0xbcc83dfb,0x3da23dc6,0xbde23d71,0x3d443ded,0xbdd53d8e,0xbc493dff,0xbdf5bd15,
0x3d803d80,0xbdedbd44,0xbdd53d8e,0xbcc8bdfb,0x3db53db5,0x3d44bded,0xbd8ebdd5,0x3dfbbcc8,0xbdb53db5,0x3ded3d44,0x3dd5bd8e,0x3cc83dfb,0xbdb5bdb5,0xbd443ded,0x3d8e3dd5,0xbdfb3cc8,
0xbd803d80,0x3dd53d8e,0x3de2bd71,0xbc493dff,0xbd443ded,0xbdfb3cc8,0xbd153df5,0xbda2bdc6,0xbd44bded,0x3d8ebdd5,0xbd71bde2,0x3dff3c49,0x3ded3d44,0x3cc83dfb,0x3df53d15,0xbdc63da2,
0x3d803d80,0xbdb5bdb5,0xbded3d44,0x3d44bded,0xbe000000,0x3db53db5,0x3dedbd44,0xbd443ded,0x3e000000,0xbdb5bdb5,0xbded3d44,0x3d44bded,0xbe000000,0x3db53db5,0x3dedbd44,0xbd443ded,
0xbd803d80,0x3d8e3dd5,0x3df5bd15,0xbda23dc6,0xbd44bded,0x3cc8bdfb,0xbde2bd71,0x3dffbc49,0xbd443ded,0xbdd53d8e,0x3d153df5,0xbdc6bda2,0x3dedbd44,0x3dfb3cc8,0x3d71bde2,0x3c493dff,
0x3d803d80,0xbd44bded,0xbdfb3cc8,0x3dd5bd8e,0x3db5bdb5,0xbded3d44,0x3cc83dfb,0xbd8ebdd5,0xbdb5bdb5,0x3d443ded,0x3dfbbcc8,0xbdd53d8e,0xbdb53db5,0x3dedbd44,0xbcc8bdfb,0x3d8e3dd5,
0xbd803d80,0x3cc83dfb,0x3dffbc49,0xbdf53d15,0x3ded3d44,0x3dd53d8e,0x3da2bdc6,0xbd713de2,0x3dedbd44,0x3dfbbcc8,0xbc49bdff,0x3d153df5,0x3d44bded,0x3d8ebdd5,0xbdc6bda2,0x3de23d71,
0x3d803d80,0xbe00,0xbe000000,0x3e000000,0x3e00,0xbe00,0xbe000000,0x3e000000,0x3e00,0xbe00,0xbe000000,0x3e000000,0x3e00,0xbe00,0xbe000000,0x3e000000,
0xbd803d80,0xbcc83dfb,0x3dff3c49,0xbdf5bd15,0xbded3d44,0xbdd53d8e,0x3da23dc6,0xbd71bde2,0xbdedbd44,0xbdfbbcc8,0xbc493dff,0x3d15bdf5,0xbd44bded,0xbd8ebdd5,0xbdc63da2,0x3de2bd71,
0x3d803d80,0x3d44bded,0xbdfbbcc8,0x3dd53d8e,0xbdb5bdb5,0x3ded3d44,0x3cc8bdfb,0xbd8e3dd5,0x3db5bdb5,0xbd443ded,0x3dfb3cc8,0xbdd5bd8e,0x3db53db5,0xbdedbd44,0xbcc83dfb,0x3d8ebdd5,
0xbd803d80,0xbd8e3dd5,0x3df53d15,0xbda2bdc6,0x3d44bded,0xbcc8bdfb,0xbde23d71,0x3dff3c49,0x3d443ded,0x3dd53d8e,0x3d15bdf5,0xbdc63da2,0xbdedbd44,0xbdfb3cc8,0x3d713de2,0x3c49bdff,
0x3d803d80,0x3db5bdb5,0xbdedbd44,0x3d443ded,0x3e000000,0xbdb53db5,0x3ded3d44,0xbd44bded,0xbe000000,0x3db5bdb5,0xbdedbd44,0x3d443ded,0x3e000000,0xbdb53db5,0x3ded3d44,0xbd44bded,
0xbd803d80,0xbdd53d8e,0x3de23d71,0xbc49bdff,0x3d443ded,0x3dfb3cc8,0xbd15bdf5,0xbda23dc6,0x3d44bded,0xbd8ebdd5,0xbd713de2,0x3dffbc49,0xbded3d44,0xbcc83dfb,0x3df5bd15,0xbdc6bda2,
0x3d803d80,0x3dedbd44,0xbdd5bd8e,0xbcc83dfb,0xbdb53db5,0xbd44bded,0xbd8e3dd5,0x3dfb3cc8,0x3db53db5,0xbded3d44,0x3dd53d8e,0x3cc8bdfb,0x3db5bdb5,0x3d443ded,0x3d8ebdd5,0xbdfbbcc8,
0xbd803d80,0xbdfb3cc8,0x3dc63da2,0x3d71bde2,0xbdedbd44,0xbd8e3dd5,0x3dffbc49,0xbd15bdf5,0xbded3d44,0x3cc83dfb,0x3da2bdc6,0xbde2bd71,0xbd443ded,0x3dd53d8e,0xbc49bdff,0xbdf53d15,
0x3d803d80,0x3e000000,0xbdb5bdb5,0xbdb53db5,0xbe00,0x3e000000,0xbdb5bdb5,0xbdb53db5,0xbe00,0x3e000000,0xbdb5bdb5,0xbdb53db5,0xbe00,0x3e000000,0xbdb5bdb5,0xbdb53db5,
0xbd803d80,0xbdfbbcc8,0x3da23dc6,0x3de2bd71,0x3dedbd44,0xbd8ebdd5,0xbc493dff,0x3df53d15,0x3ded3d44,0x3cc8bdfb,0xbdc63da2,0x3d713de2,0x3d443ded,0x3dd5bd8e,0xbdffbc49,0xbd153df5,
0x3d803d80,0x3ded3d44,0xbd8ebdd5,0xbdfb3cc8,0x3db53db5,0xbd443ded,0x3dd5bd8e,0xbcc8bdfb,0xbdb53db5,0xbdedbd44,0x3d8e3dd5,0x3dfbbcc8,0xbdb5bdb5,0x3d44bded,0xbdd53d8e,0x3cc83dfb,
0xbd803d80,0xbdd5bd8e,0x3d713de2,0x3dff3c49,0xbd443ded,0x3dfbbcc8,0xbdf5bd15,0xbdc63da2,0xbd44bded,0xbd8e3dd5,0x3de2bd71,0x3c49bdff,0x3ded3d44,0xbcc8bdfb,0xbd153df5,0x3da23dc6,
0x3d803d80,0x3db53db5,0xbd44bded,0xbdedbd44,0xbe000000,0xbdb5bdb5,0x3d443ded,0x3ded3d44,0x3e000000,0x3db53db5,0xbd44bded,0xbdedbd44,0xbe000000,0xbdb5bdb5,0x3d443ded,0x3ded3d44,
0xbd803d80,0xbd8ebdd5,0x3d153df5,0x3dc63da2,0xbd44bded,0xbcc83dfb,0x3d71bde2,0xbc49bdff,0xbd443ded,0x3dd5bd8e,0xbdf53d15,0xbda23dc6,0x3dedbd44,0xbdfbbcc8,0x3de23d71,0x3dffbc49,
0x3d803d80,0x3d443ded,0xbcc8bdfb,0xbd8ebdd5,0x3db5bdb5,0x3dedbd44,0xbdfb3cc8,0xbdd53d8e,0xbdb5bdb5,0xbd44bded,0x3cc83dfb,0x3d8e3dd5,0xbdb53db5,0xbded3d44,0x3dfbbcc8,0x3dd5bd8e,
0xbd803d80,0xbcc8bdfb,0x3c493dff,0x3d153df5,0x3ded3d44,0xbdd5bd8e,0x3dc63da2,0x3de23d71,0x3dedbd44,0xbdfb3cc8,0x3dffbc49,0x3df5bd15,0x3d44bded,0xbd8e3dd5,0x3da2bdc6,0x3d71bde2,
0xbc493dff,0xbbc93e00,0xbb493e00,0xbc173dff,0xbcc83dfb,0xbcf93df8,0xbce03dfa,0xbd093df7,0xbd443ded,0xbd5b3de7,0xbd4f3dea,0xbd663de5,0xbd8e3dd5,0xbd983dce,0xbd933dd1,0xbd9d3dca,
0xbd713de2,0xbcf93df8,0xbc7b3dfe,0xbd383def,0xbdd53d8e,0xbdf13d2c,0xbde53d66,0xbdfa3ce0,0xbdedbd44,0xbdcebd98,0xbddfbd7c,0xbdb9bdb1,0xbcc8bdfb,0x3bc9be00,0xbc17bdff,0x3cafbdfc,
0xbdc63da2,0xbd5b3de7,0xbce03dfa,0xbd9d3dca,0xbdfbbcc8,0xbdcebd98,0xbdeabd4f,0xbda7bdc2,0x3d44bded,0x3dbebdac,0x3d93bdd1,0x3ddfbd7c,0x3dd53d8e,0x3d843ddc,0x3db13db9,0x3d213df3,
0xbdf53d15,0xbd983dce,0xbd213df3,0xbdd13d93,0xbd8ebdd5,0x3bc9be00,0xbd09bdf7,0x3d38bdef,0x3ded3d44,0x3d843ddc,0x3dc23da7,0x3ce03dfa,0xbdfb3cc8,0xbde7bd5b,0xbdfebc7b,0xbdb9bdb1,
0xbdffbc49,0xbdbe3dac,0xbd4f3dea,0xbdf33d21,0x3cc8bdfb,0x3ddcbd84,0x3d93bdd1,0x3dfebc7b,0xbd443ded,0xbdf13d2c,0xbdb93db1,0xbdffbc17,0x3d8ebdd5,0x3dfdbc96,0x3dd8bd89,0x3df73d09,
0xbde2bd71,0xbddc3d84,0xbd7c3ddf,0xbe003b49,0x3dd5bd8e,0x3de73d5b,0x3dffbc17,0x3d933dd1,0xbdedbd44,0xbc96bdfd,0xbd9dbdca,0x3d38bdef,0x3cc83dfb,0xbdbe3dac,0xbd213df3,0xbdfa3ce0,
0xbda2bdc6,0xbdf13d2c,0xbd933dd1,0xbdf7bd09,0x3dfb3cc8,0x3c963dfd,0x3db13db9,0xbd663de5,0x3d44bded,0x3e003bc9,0x3dd8bd89,0x3dca3d9d,0xbdd5bd8e,0x3cf9bdf8,0xbd38bdef,0x3dc2bda7,
0xbd15bdf5,0xbdfd3c96,0xbda73dc2,0xbdd8bd89,0x3d8e3dd5,0xbdbe3dac,0xbc7b3dfe,0xbe003b49,0x3ded3d44,0xbcf93df8,0x3d663de5,0xbdd13d93,0x3dfbbcc8,0x3d2c3df1,0x3ddf3d7c,0xbd383def,
0x3c49bdff,0xbe00bbc9,0xbdb93db1,0xbda7bdc2,0xbcc83dfb,0xbdf8bcf9,0xbdd83d89,0xbd7cbddf,0xbd443ded,0xbde7bd5b,0xbdef3d38,0xbd21bdf3,0xbd8e3dd5,0xbdcebd98,0xbdfc3caf,0xbc7bbdfe,
0x3d71bde2,0xbdf8bcf9,0xbdca3d9d,0xbd4fbdea,0xbdd53d8e,0xbd2cbdf1,0xbdf3bd21,0x3d89bdd8,0xbdedbd44,0x3d98bdce,0xbd09bdf7,0x3e00bb49,0xbcc8bdfb,0x3e003bc9,0x3da7bdc2,0x3d933dd1,
0x3dc6bda2,0xbde7bd5b,0xbdd83d89,0xbc7bbdfe,0xbdfbbcc8,0x3d98bdce,0xbd38bdef,0x3dff3c17,0x3d44bded,0x3dac3dbe,0x3dfcbcaf,0xbd093df7,0x3dd53d8e,0xbddc3d84,0xbb493e00,0xbde5bd66,
0x3df5bd15,0xbdcebd98,0xbde53d66,0x3cafbdfc,0xbd8ebdd5,0x3e003bc9,0x3d7cbddf,0x3d4f3dea,0x3ded3d44,0xbddc3d84,0x3c173dff,0xbdd8bd89,0xbdfb3cc8,0x3d5bbde7,0xbd9dbdca,0x3e00bb49,
0x3dff3c49,0xbdacbdbe,0xbdef3d38,0x3d66bde5,0x3cc8bdfb,0x3d843ddc,0x3dfcbcaf,0xbd9d3dca,0xbd443ded,0xbd2cbdf1,0xbe00bb49,0x3dc2bda7,0x3d8ebdd5,0x3c963dfd,0x3dfa3ce0,0xbddf3d7c,
0x3de23d71,0xbd84bddc,0xbdf73d09,0x3db1bdb9,0x3dd5bd8e,0xbd5b3de7,0x3dc23da7,0xbdfcbcaf,0xbdedbd44,0x3dfdbc96,0x3c7bbdfe,0x3d4f3dea,0x3cc83dfb,0xbdacbdbe,0xbde53d66,0x3d89bdd8,
0x3da23dc6,0xbd2cbdf1,0xbdfc3caf,0x3ddfbd7c,0x3dfb3cc8,0xbdfd3c96,0xbb493e00,0xbd21bdf3,0x3d44bded,0xbbc93e00,0x3dfa3ce0,0xbdfe3c7b,0xbdd5bd8e,0x3df83cf9,0x3d4fbdea,0xbc173dff,
0x3d153df5,0xbc96bdfd,0xbdff3c17,0x3dfabce0,0x3d8e3dd5,0xbdacbdbe,0xbdca3d9d,0x3db1bdb9,0x3ded3d44,0xbdf8bcf9,0xbd213df3,0x3cafbdfc,0x3dfbbcc8,0xbdf13d2c,0x3d093df7,0xbd4fbdea,
0xbc493dff,0x3bc9be00,0xbe00bb49,0x3dff3c17,0xbcc83dfb,0x3cf9bdf8,0xbdfabce0,0x3df73d09,0xbd443ded,0x3d5bbde7,0xbdeabd4f,0x3de53d66,0xbd8e3dd5,0x3d98bdce,0xbdd1bd93,0x3dca3d9d,
0xbd713de2,0x3cf9bdf8,0xbdfebc7b,0x3def3d38,0xbdd53d8e,0x3df1bd2c,0xbd66bde5,0x3ce03dfa,0xbdedbd44,0x3dce3d98,0x3d7cbddf,0xbdb13db9,0xbcc8bdfb,0xbbc93e00,0x3dffbc17,0xbdfcbcaf,
0xbdc63da2,0x3d5bbde7,0xbdfabce0,0x3dca3d9d,0xbdfbbcc8,0x3dce3d98,0x3d4fbdea,0xbdc23da7,0x3d44bded,0xbdbe3dac,0x3dd13d93,0xbd7cbddf,0x3dd53d8e,0xbd84bddc,0xbdb93db1,0x3df3bd21,
0xbdf53d15,0x3d98bdce,0xbdf3bd21,0x3d933dd1,0xbd8ebdd5,0xbbc93e00,0x3df7bd09,0xbdefbd38,0x3ded3d44,0xbd84bddc,0xbda73dc2,0x3dfabce0,0xbdfb3cc8,0x3de73d5b,0x3c7bbdfe,0xbdb13db9,
0xbdffbc49,0x3dbebdac,0xbdeabd4f,0x3d213df3,0x3cc8bdfb,0xbddc3d84,0x3dd13d93,0xbc7bbdfe,0xbd443ded,0x3df1bd2c,0xbdb1bdb9,0xbc173dff,0x3d8ebdd5,0xbdfd3c96,0x3d893dd8,0x3d09bdf7,
0xbde2bd71,0x3ddcbd84,0xbddfbd7c,0x3b493e00,0x3dd5bd8e,0xbde7bd5b,0x3c173dff,0x3dd1bd93,0xbdedbd44,0x3c963dfd,0x3dcabd9d,0xbdefbd38,0x3cc83dfb,0x3dbebdac,0xbdf3bd21,0x3ce03dfa,
0xbda2bdc6,0x3df1bd2c,0xbdd1bd93,0xbd093df7,0x3dfb3cc8,0xbc96bdfd,0xbdb93db1,0x3de53d66,0x3d44bded,0xbe00bbc9,0x3d893dd8,0x3d9dbdca,0xbdd5bd8e,0xbcf93df8,0x3defbd38,0xbda7bdc2,
0xbd15bdf5,0x3dfdbc96,0xbdc2bda7,0xbd893dd8,0x3d8e3dd5,0x3dbebdac,0xbdfebc7b,0x3b493e00,0x3ded3d44,0x3cf9bdf8,0xbde53d66,0x3d933dd1,0x3dfbbcc8,0xbd2cbdf1,0xbd7c3ddf,0x3def3d38,
0x3c49bdff,0x3e003bc9,0xbdb1bdb9,0xbdc23da7,0xbcc83dfb,0x3df83cf9,0xbd89bdd8,0xbddf3d7c,0xbd443ded,0x3de73d5b,0xbd38bdef,0xbdf33d21,0xbd8e3dd5,0x3dce3d98,0xbcafbdfc,0xbdfe3c7b,
0x3d71bde2,0x3df83cf9,0xbd9dbdca,0xbdea3d4f,0xbdd53d8e,0x3d2c3df1,0x3d21bdf3,0xbdd8bd89,0xbdedbd44,0xbd983dce,0x3df7bd09,0xbb49be00,0xbcc8bdfb,0xbe00bbc9,0x3dc23da7,0x3dd1bd93,
0x3dc6bda2,0x3de73d5b,0xbd89bdd8,0xbdfe3c7b,0xbdfbbcc8,0xbd983dce,0x3defbd38,0x3c17bdff,0x3d44bded,0xbdacbdbe,0x3caf3dfc,0x3df73d09,0x3dd53d8e,0x3ddcbd84,0xbe00bb49,0xbd663de5,
0x3df5bd15,0x3dce3d98,0xbd66bde5,0xbdfcbcaf,0xbd8ebdd5,0xbe00bbc9,0x3ddf3d7c,0x3deabd4f,0x3ded3d44,0x3ddcbd84,0xbdff3c17,0xbd893dd8,0xbdfb3cc8,0xbd5b3de7,0x3dcabd9d,0xbb49be00,
0x3dff3c49,0x3dac3dbe,0xbd38bdef,0xbde5bd66,0x3cc8bdfb,0xbd84bddc,0x3caf3dfc,0x3dca3d9d,0xbd443ded,0x3d2c3df1,0x3b49be00,0xbda7bdc2,0x3d8ebdd5,0xbc96bdfd,0xbce03dfa,0x3d7c3ddf,
0x3de23d71,0x3d843ddc,0xbd09bdf7,0xbdb9bdb1,0x3dd5bd8e,0x3d5bbde7,0xbda73dc2,0xbcaf3dfc,0xbdedbd44,0xbdfd3c96,0x3dfe3c7b,0x3deabd4f,0x3cc83dfb,0x3dac3dbe,0xbd66bde5,0xbdd8bd89,
0x3da23dc6,0x3d2c3df1,0xbcafbdfc,0xbd7cbddf,0x3dfb3cc8,0x3dfdbc96,0xbe00bb49,0xbdf33d21,0x3d44bded,0x3bc9be00,0xbce03dfa,0x3c7b3dfe,0xbdd5bd8e,0xbdf8bcf9,0x3dea3d4f,0x3dff3c17,
0x3d153df5,0x3c963dfd,0xbc17bdff,0xbce0bdfa,0x3d8e3dd5,0x3dac3dbe,0xbd9dbdca,0xbdb9bdb1,0x3ded3d44,0x3df83cf9,0xbdf3bd21,0xbdfcbcaf,0x3dfbbcc8,0x3df1bd2c,0xbdf73d09,0xbdea3d4f,
0xbdb53d80,0xbdbe3dac,0xbdb93db1,0xbdc23da7,0xbd153df5,0xbddc3d84,0xbdd83d89,0xbddf3d7c,0xbd713de2,0xbdf13d2c,0xbdef3d38,0xbdf33d21,0xbda23dc6,0xbdfd3c96,0xbdfc3caf,0xbdfe3c7b,
0x3db53d80,0x3ddcbd84,0x3dcabd9d,0x3deabd4f,0xbdff3c49,0x3de73d5b,0x3df33d21,0x3dd83d89,0xbda2bdc6,0x3c963dfd,0x3d093df7,0x3b493e00,0x3d15bdf5,0xbdbe3dac,0xbda73dc2,0xbdd13d93,
0xbdb53d80,0xbdf13d2c,0xbdd83d89,0xbdfe3c7b,0xbd71bde2,0xbc96bdfd,0xbd38bdef,0x3c17bdff,0x3df5bd15,0x3e003bc9,0x3dfcbcaf,0x3df73d09,0x3c493dff,0xbcf93df8,0xbb493e00,0xbd663de5,
0x3db53d80,0x3dfdbc96,0x3de5bd66,0x3dfc3caf,0x3da2bdc6,0xbdbe3dac,0xbd7c3ddf,0xbdea3d4f,0xbc493dff,0x3cf9bdf8,0xbc17bdff,0x3d89bdd8,0xbd71bde2,0x3d2c3df1,0x3d9d3dca,0x3b493e00,
0xbdb53d80,0xbe00bbc9,0xbdef3d38,0xbde5bd66,0x3df53d15,0x3df83cf9,0x3dfcbcaf,0x3dca3d9d,0xbde2bd71,0xbde7bd5b,0xbe00bb49,0xbda7bdc2,0x3dc63da2,0x3dce3d98,0x3dfa3ce0,0x3d7c3ddf,
0x3db53d80,0x3df83cf9,0x3df7bd09,0x3db93db1,0x3c493dff,0xbd2cbdf1,0xbdc2bda7,0x3cafbdfc,0x3dc6bda2,0xbd983dce,0xbc7b3dfe,0xbdea3d4f,0xbdf5bd15,0x3e003bc9,0x3de5bd66,0x3dd83d89,
0xbdb53d80,0xbde7bd5b,0xbdfc3caf,0xbd7cbddf,0xbde23d71,0xbd983dce,0xbb493e00,0xbdf33d21,0x3d153df5,0x3dac3dbe,0x3dfa3ce0,0x3c7b3dfe,0x3dffbc49,0x3ddcbd84,0x3d4fbdea,0x3dff3c17,
0x3db53d80,0x3dce3d98,0x3dffbc17,0x3ce03dfa,0xbdc6bda2,0x3e003bc9,0x3dcabd9d,0x3db93db1,0xbdffbc49,0x3ddcbd84,0x3d21bdf3,0x3dfc3caf,0xbde23d71,0x3d5bbde7,0xbd09bdf7,0x3deabd4f,
0xbdb53d80,0xbdacbdbe,0xbe00bb49,0x3c17bdff,0x3d15bdf5,0xbd84bddc,0xbdfabce0,0x3d09bdf7,0x3d71bde2,0xbd2cbdf1,0xbdeabd4f,0x3d66bde5,0x3da2bdc6,0xbc96bdfd,0xbdd1bd93,0x3d9dbdca,
0x3db53d80,0x3d843ddc,0x3dfe3c7b,0xbd383def,0x3dffbc49,0xbd5b3de7,0x3d663de5,0xbdfa3ce0,0x3da23dc6,0xbdfd3c96,0xbd7c3ddf,0xbdb9bdb1,0xbd153df5,0xbdacbdbe,0xbdff3c17,0x3cafbdfc,
0xbdb53d80,0xbd2cbdf1,0xbdfabce0,0x3d9dbdca,0x3d713de2,0x3dfdbc96,0x3d4fbdea,0x3da73dc2,0xbdf53d15,0xbbc93e00,0x3dd13d93,0xbddf3d7c,0xbc49bdff,0xbdf8bcf9,0xbdb93db1,0xbd21bdf3,
0x3db53d80,0x3c963dfd,0x3df33d21,0xbdd13d93,0xbda23dc6,0xbdacbdbe,0xbdf73d09,0x3d38bdef,0x3c49bdff,0x3df83cf9,0x3da7bdc2,0x3ce03dfa,0x3d713de2,0xbdf13d2c,0xbc7b3dfe,0xbdb9bdb1,
0xbdb53d80,0x3bc9be00,0xbdeabd4f,0x3df3bd21,0xbdf5bd15,0xbcf93df8,0x3dd13d93,0xbdfe3c7b,0x3de23d71,0x3d5bbde7,0xbdb1bdb9,0x3dff3c17,0xbdc6bda2,0xbd983dce,0x3d893dd8,0xbdf7bd09,
0x3db53d80,0xbcf93df8,0x3ddf3d7c,0xbe003b49,0xbc49bdff,0x3df1bd2c,0xbc17bdff,0x3d933dd1,0xbdc63da2,0xbdcebd98,0xbdca3d9d,0x3d38bdef,0x3df53d15,0xbbc93e00,0x3df33d21,0xbdfa3ce0,
0xbdb53d80,0x3d5bbde7,0xbdd1bd93,0x3df73d09,0x3de2bd71,0xbdcebd98,0xbdb93db1,0x3d66bde5,0xbd15bdf5,0xbdbe3dac,0x3d893dd8,0xbdcabd9d,0xbdff3c49,0x3d843ddc,0x3defbd38,0xbdc23da7,
0x3db53d80,0xbd983dce,0x3dc23da7,0xbdd8bd89,0x3dc63da2,0xbbc93e00,0x3dfe3c7b,0xbe003b49,0x3dff3c49,0x3d843ddc,0x3de5bd66,0xbdd13d93,0x3de2bd71,0x3de73d5b,0x3d7cbddf,0xbd383def,
0xbdb53d80,0x3dbebdac,0xbdb1bdb9,0x3da73dc2,0xbd153df5,0x3ddcbd84,0xbd89bdd8,0x3d7c3ddf,0xbd713de2,0x3df1bd2c,0xbd38bdef,0x3d213df3,0xbda23dc6,0x3dfdbc96,0xbcafbdfc,0x3c7b3dfe,
0x3db53d80,0xbddc3d84,0x3d9d3dca,0xbd4fbdea,0xbdff3c49,0xbde7bd5b,0xbd213df3,0x3d89bdd8,0xbda2bdc6,0xbc96bdfd,0xbdf73d09,0x3e00bb49,0x3d15bdf5,0x3dbebdac,0xbdc2bda7,0x3d933dd1,
0xbdb53d80,0x3df1bd2c,0xbd89bdd8,0x3c7b3dfe,0xbd71bde2,0x3c963dfd,0x3defbd38,0xbdffbc17,0x3df5bd15,0xbe00bbc9,0x3caf3dfc,0x3d09bdf7,0x3c493dff,0x3cf9bdf8,0xbe00bb49,0x3de53d66,
0x3db53d80,0xbdfd3c96,0x3d663de5,0x3cafbdfc,0x3da2bdc6,0x3dbebdac,0xbddfbd7c,0x3d4f3dea,0xbc493dff,0xbcf93df8,0x3dffbc17,0xbdd8bd89,0xbd71bde2,0xbd2cbdf1,0xbdca3d9d,0x3e00bb49,
0xbdb53d80,0x3e003bc9,0xbd38bdef,0xbd663de5,0x3df53d15,0xbdf8bcf9,0x3caf3dfc,0x3d9dbdca,0xbde2bd71,0x3de73d5b,0x3b49be00,0xbdc23da7,0x3dc63da2,0xbdcebd98,0xbce03dfa,0x3ddfbd7c,
0x3db53d80,0xbdf8bcf9,0x3d093df7,0x3db1bdb9,0x3c493dff,0x3d2c3df1,0x3da7bdc2,0xbdfcbcaf,0x3dc6bda2,0x3d98bdce,0xbdfebc7b,0x3d4f3dea,0xbdf5bd15,0xbe00bbc9,0x3d663de5,0x3d89bdd8,
0xbdb53d80,0x3de73d5b,0xbcafbdfc,0xbddf3d7c,0xbde23d71,0x3d98bdce,0xbe00bb49,0x3d213df3,0x3d153df5,0xbdacbdbe,0xbce03dfa,0x3dfebc7b,0x3dffbc49,0xbddc3d84,0x3dea3d4f,0x3c17bdff,
0x3db53d80,0xbdcebd98,0x3c173dff,0x3dfabce0,0xbdc6bda2,0xbe00bbc9,0x3d9d3dca,0x3db1bdb9,0xbdffbc49,0xbddc3d84,0x3df33d21,0x3cafbdfc,0xbde23d71,0xbd5b3de7,0x3df7bd09,0xbd4fbdea,
0xbdb53d80,0x3dac3dbe,0x3b49be00,0xbdffbc17,0x3d15bdf5,0x3d843ddc,0x3ce0bdfa,0xbdf7bd09,0x3d71bde2,0x3d2c3df1,0x3d4fbdea,0xbde5bd66,0x3da2bdc6,0x3c963dfd,0x3d93bdd1,0xbdcabd9d,
0x3db53d80,0xbd84bddc,0xbc7b3dfe,0x3def3d38,0x3dffbc49,0x3d5bbde7,0xbde53d66,0x3ce03dfa,0x3da23dc6,0x3dfdbc96,0xbddfbd7c,0xbdb13db9,0xbd153df5,0x3dac3dbe,0xbc17bdff,0xbdfcbcaf,
0xbdb53d80,0x3d2c3df1,0x3ce0bdfa,0xbdcabd9d,0x3d713de2,0xbdfd3c96,0x3dea3d4f,0x3dc2bda7,0xbdf53d15,0x3bc9be00,0xbd933dd1,0x3d7c3ddf,0xbc49bdff,0x3df83cf9,0xbdb1bdb9,0xbdf33d21,
0x3db53d80,0xbc96bdfd,0xbd213df3,0x3d933dd1,0xbda23dc6,0x3dac3dbe,0xbd09bdf7,0xbdefbd38,0x3c49bdff,0xbdf8bcf9,0x3dc23da7,0x3dfabce0,0x3d713de2,0x3df1bd2c,0xbdfebc7b,0xbdb13db9,
0xbdb53d80,0xbbc93e00,0x3d4fbdea,0xbd21bdf3,0xbdf5bd15,0x3cf9bdf8,0xbd933dd1,0x3c7b3dfe,0x3de23d71,0xbd5b3de7,0x3db9bdb1,0x3c17bdff,0xbdc6bda2,0x3d98bdce,0xbdd83d89,0xbd093df7,
0x3db53d80,0x3cf9bdf8,0xbd7c3ddf,0x3b493e00,0xbc49bdff,0xbdf13d2c,0x3dffbc17,0x3dd1bd93,0xbdc63da2,0x3dce3d98,0xbd9dbdca,0xbdefbd38,0x3df53d15,0x3bc9be00,0xbd213df3,0x3ce03dfa,
0xbdb53d80,0xbd5b3de7,0x3d93bdd1,0x3d09bdf7,0x3de2bd71,0x3dce3d98,0xbdb1bdb9,0xbde5bd66,0xbd15bdf5,0x3dbebdac,0xbdd83d89,0xbd9d3dca,0xbdff3c49,0xbd84bddc,0x3d383def,0x3da73dc2,
0x3db53d80,0x3d98bdce,0xbda73dc2,0xbd893dd8,0x3dc63da2,0x3bc9be00,0xbc7b3dfe,0x3b493e00,0x3dff3c49,0xbd84bddc,0x3d663de5,0x3d933dd1,0x3de2bd71,0xbde7bd5b,0x3ddf3d7c,0x3def3d38,
0xbcc83dfb,0xbc493dff,0xbbc93e00,0xbc963dfd,0xbd443ded,0xbd713de2,0xbd5b3de7,0xbd843ddc,0xbdb53db5,0xbdc63da2,0xbdbe3dac,0xbdce3d98,0xbded3d44,0xbdf53d15,0xbdf13d2c,0xbdf83cf9,
0xbd8e3dd5,0xbd153df5,0xbc963dfd,0xbd5b3de7,0xbded3d44,0xbdff3c49,0xbdf83cf9,0xbe00bbc9,0xbdb5bdb5,0xbd71bde2,0xbd98bdce,0xbd2cbdf1,0x3d44bded,0x3da2bdc6,0x3d84bddc,0x3dbebdac,
0xbdd53d8e,0xbd713de2,0xbcf93df8,0xbdac3dbe,0xbdedbd44,0xbda2bdc6,0xbdcebd98,0xbd5bbde7,0x3db5bdb5,0x3df5bd15,0x3ddcbd84,0x3e00bbc9,0x3d443ded,0xbc493dff,0x3c963dfd,0xbd2c3df1,
0xbdfb3cc8,0xbda23dc6,0xbd2c3df1,0xbddc3d84,0xbd44bded,0x3d15bdf5,0xbbc9be00,0x3d98bdce,0x3db53db5,0x3c493dff,0x3d5b3de7,0xbcf93df8,0xbdedbd44,0xbd71bde2,0xbdbebdac,0xbc96bdfd,
0xbdfbbcc8,0xbdc63da2,0xbd5b3de7,0xbdf83cf9,0x3d44bded,0x3df5bd15,0x3dbebdac,0x3dfd3c96,0xbdb53db5,0xbdffbc49,0xbdf13d2c,0xbddcbd84,0x3dedbd44,0x3de23d71,0x3e003bc9,0x3d983dce,
0xbdd5bd8e,0xbde23d71,0xbd843ddc,0xbe00bbc9,0x3dedbd44,0x3dc63da2,0x3dfd3c96,0x3d2c3df1,0xbdb5bdb5,0x3d15bdf5,0xbcf9bdf8,0x3dbebdac,0xbd443ded,0xbdff3c49,0xbdce3d98,0xbde7bd5b,
0xbd8ebdd5,0xbdf53d15,0xbd983dce,0xbdf1bd2c,0x3ded3d44,0xbc493dff,0x3d843ddc,0xbdac3dbe,0x3db5bdb5,0x3de23d71,0x3dfdbc96,0x3d5b3de7,0xbd44bded,0x3dc6bda2,0x3cf9bdf8,0x3e00bbc9,
0xbcc8bdfb,0xbdff3c49,0xbdac3dbe,0xbdcebd98,0x3d443ded,0xbde23d71,0xbd2c3df1,0xbdf8bcf9,0x3db53db5,0xbda23dc6,0x3bc93e00,0xbdfd3c96,0x3ded3d44,0xbd153df5,0x3d5b3de7,0xbddc3d84,
0x3cc8bdfb,0xbdffbc49,0xbdbe3dac,0xbd98bdce,0xbd443ded,0xbde2bd71,0xbdf13d2c,0xbcf9bdf8,0xbdb53db5,0xbda2bdc6,0xbe00bbc9,0x3c96bdfd,0xbded3d44,0xbd15bdf5,0xbde7bd5b,0x3d84bddc,
0x3d8ebdd5,0xbdf5bd15,0xbdce3d98,0xbd2cbdf1,0xbded3d44,0xbc49bdff,0xbddcbd84,0x3dbebdac,0xbdb5bdb5,0x3de2bd71,0x3c96bdfd,0x3de73d5b,0x3d44bded,0x3dc63da2,0x3df8bcf9,0xbbc93e00,
0x3dd5bd8e,0xbde2bd71,0xbddc3d84,0xbbc9be00,0xbdedbd44,0x3dc6bda2,0xbc96bdfd,0x3df13d2c,0x3db5bdb5,0x3d153df5,0x3df83cf9,0xbdac3dbe,0x3d443ded,0xbdffbc49,0xbd983dce,0xbd5bbde7,
0x3dfbbcc8,0xbdc6bda2,0xbde73d5b,0x3cf9bdf8,0xbd44bded,0x3df53d15,0x3dacbdbe,0x3c963dfd,0x3db53db5,0xbdff3c49,0xbd2c3df1,0xbd84bddc,0xbdedbd44,0x3de2bd71,0xbbc9be00,0x3dce3d98,
0x3dfb3cc8,0xbda2bdc6,0xbdf13d2c,0x3d84bddc,0x3d44bded,0x3d153df5,0x3e003bc9,0xbdce3d98,0xbdb53db5,0x3c49bdff,0xbde7bd5b,0x3df8bcf9,0x3dedbd44,0xbd713de2,0x3dac3dbe,0xbdfdbc96,
0x3dd53d8e,0xbd71bde2,0xbdf83cf9,0x3dbebdac,0x3dedbd44,0xbda23dc6,0x3d983dce,0xbde7bd5b,0xbdb5bdb5,0x3df53d15,0x3d84bddc,0xbbc93e00,0xbd443ded,0xbc49bdff,0xbdfdbc96,0x3df1bd2c,
0x3d8e3dd5,0xbd15bdf5,0xbdfd3c96,0x3de7bd5b,0x3ded3d44,0xbdffbc49,0xbcf93df8,0xbbc9be00,0x3db5bdb5,0xbd713de2,0x3dce3d98,0xbdf1bd2c,0xbd44bded,0x3da23dc6,0x3ddcbd84,0xbdac3dbe,
0x3cc83dfb,0xbc49bdff,0xbe003bc9,0x3dfdbc96,0x3d443ded,0xbd71bde2,0xbde73d5b,0x3ddcbd84,0x3db53db5,0xbdc6bda2,0xbdac3dbe,0x3d98bdce,0x3ded3d44,0xbdf5bd15,0xbd2c3df1,0x3cf9bdf8,
0xbcc83dfb,0x3c49bdff,0xbe00bbc9,0x3dfd3c96,0xbd443ded,0x3d71bde2,0xbde7bd5b,0x3ddc3d84,0xbdb53db5,0x3dc6bda2,0xbdacbdbe,0x3d983dce,0xbded3d44,0x3df5bd15,0xbd2cbdf1,0x3cf93df8,
0xbd8e3dd5,0x3d15bdf5,0xbdfdbc96,0x3de73d5b,0xbded3d44,0x3dffbc49,0xbcf9bdf8,0xbbc93e00,0xbdb5bdb5,0x3d713de2,0x3dcebd98,0xbdf13d2c,0x3d44bded,0xbda23dc6,0x3ddc3d84,0xbdacbdbe,
0xbdd53d8e,0x3d71bde2,0xbdf8bcf9,0x3dbe3dac,0xbdedbd44,0x3da23dc6,0x3d98bdce,0xbde73d5b,0x3db5bdb5,0xbdf53d15,0x3d843ddc,0xbbc9be00,0x3d443ded,0x3c49bdff,0xbdfd3c96,0x3df13d2c,
0xbdfb3cc8,0x3da2bdc6,0xbdf1bd2c,0x3d843ddc,0xbd44bded,0xbd153df5,0x3e00bbc9,0xbdcebd98,0x3db53db5,0xbc49bdff,0xbde73d5b,0x3df83cf9,0xbdedbd44,0x3d713de2,0x3dacbdbe,0xbdfd3c96,
0xbdfbbcc8,0x3dc6bda2,0xbde7bd5b,0x3cf93df8,0x3d44bded,0xbdf53d15,0x3dac3dbe,0x3c96bdfd,0xbdb53db5,0x3dff3c49,0xbd2cbdf1,0xbd843ddc,0x3dedbd44,0xbde2bd71,0xbbc93e00,0x3dcebd98,
0xbdd5bd8e,0x3de2bd71,0xbddcbd84,0xbbc93e00,0x3dedbd44,0xbdc6bda2,0xbc963dfd,0x3df1bd2c,0xbdb5bdb5,0xbd153df5,0x3df8bcf9,0xbdacbdbe,0xbd443ded,0x3dffbc49,0xbd98bdce,0xbd5b3de7,
0xbd8ebdd5,0x3df5bd15,0xbdcebd98,0xbd2c3df1,0x3ded3d44,0x3c49bdff,0xbddc3d84,0x3dbe3dac,0x3db5bdb5,0xbde2bd71,0x3c963dfd,0x3de7bd5b,0xbd44bded,0xbdc63da2,0x3df83cf9,0xbbc9be00,
0xbcc8bdfb,0x3dffbc49,0xbdbebdac,0xbd983dce,0x3d443ded,0x3de2bd71,0xbdf1bd2c,0xbcf93df8,0x3db53db5,0x3da2bdc6,0xbe003bc9,0x3c963dfd,0x3ded3d44,0x3d15bdf5,0xbde73d5b,0x3d843ddc,
0x3cc8bdfb,0x3dff3c49,0xbdacbdbe,0xbdce3d98,0xbd443ded,0x3de23d71,0xbd2cbdf1,0xbdf83cf9,0xbdb53db5,0x3da23dc6,0x3bc9be00,0xbdfdbc96,0xbded3d44,0x3d153df5,0x3d5bbde7,0xbddcbd84,
0x3d8ebdd5,0x3df53d15,0xbd98bdce,0xbdf13d2c,0xbded3d44,0x3c493dff,0x3d84bddc,0xbdacbdbe,0xbdb5bdb5,0xbde23d71,0x3dfd3c96,0x3d5bbde7,0x3d44bded,0xbdc6bda2,0x3cf93df8,0x3e003bc9,
0x3dd5bd8e,0x3de23d71,0xbd84bddc,0xbe003bc9,0xbdedbd44,0xbdc63da2,0x3dfdbc96,0x3d2cbdf1,0x3db5bdb5,0xbd15bdf5,0xbcf93df8,0x3dbe3dac,0x3d443ded,0x3dff3c49,0xbdcebd98,0xbde73d5b,
0x3dfbbcc8,0x3dc63da2,0xbd5bbde7,0xbdf8bcf9,0xbd44bded,0xbdf5bd15,0x3dbe3dac,0x3dfdbc96,0x3db53db5,0x3dffbc49,0xbdf1bd2c,0xbddc3d84,0xbdedbd44,0xbde23d71,0x3e00bbc9,0x3d98bdce,
0x3dfb3cc8,0x3da23dc6,0xbd2cbdf1,0xbddcbd84,0x3d44bded,0xbd15bdf5,0xbbc93e00,0x3d983dce,0xbdb53db5,0xbc493dff,0x3d5bbde7,0xbcf9bdf8,0x3dedbd44,0x3d71bde2,0xbdbe3dac,0xbc963dfd,
0x3dd53d8e,0x3d713de2,0xbcf9bdf8,0xbdacbdbe,0x3dedbd44,0x3da2bdc6,0xbdce3d98,0xbd5b3de7,0xbdb5bdb5,0xbdf5bd15,0x3ddc3d84,0x3e003bc9,0xbd443ded,0x3c493dff,0x3c96bdfd,0xbd2cbdf1,
0x3d8e3dd5,0x3d153df5,0xbc96bdfd,0xbd5bbde7,0x3ded3d44,0x3dff3c49,0xbdf8bcf9,0xbe003bc9,0x3db5bdb5,0x3d71bde2,0xbd983dce,0xbd2c3df1,0xbd44bded,0xbda2bdc6,0x3d843ddc,0x3dbe3dac,
0x3cc83dfb,0x3c493dff,0xbbc9be00,0xbc96bdfd,0x3d443ded,0x3d713de2,0xbd5bbde7,0xbd84bddc,0x3db53db5,0x3dc63da2,0xbdbebdac,0xbdcebd98,0x3ded3d44,0x3df53d15,0xbdf1bd2c,0xbdf8bcf9,
0xbd803d80,0xbdffbc49,0xbe00bbc9,0xbdfdbc96,0xbd8e3dd5,0xbde2bd71,0xbde7bd5b,0xbddcbd84,0xbdd53d8e,0xbda2bdc6,0xbdacbdbe,0xbd98bdce,0xbdfb3cc8,0xbd15bdf5,0xbd2cbdf1,0xbcf9bdf8,
0x3d803d80,0x3df53d15,0x3dfd3c96,0x3de73d5b,0xbdfbbcc8,0x3c493dff,0x3cf93df8,0xbbc93e00,0xbcc8bdfb,0xbde23d71,0xbdce3d98,0xbdf13d2c,0x3dd5bd8e,0xbdc6bda2,0xbddcbd84,0xbdacbdbe,
0xbd803d80,0xbde2bd71,0xbdf8bcf9,0xbdbebdac,0xbcc8bdfb,0x3dc6bda2,0x3d98bdce,0x3de7bd5b,0x3dfb3cc8,0x3d153df5,0x3d843ddc,0x3bc93e00,0xbd8e3dd5,0xbdffbc49,0xbdfd3c96,0xbdf1bd2c,
0x3d803d80,0x3dc63da2,0x3df13d2c,0x3d843ddc,0x3dd5bd8e,0xbdf5bd15,0xbe003bc9,0xbdcebd98,0xbd8e3dd5,0x3dffbc49,0x3de7bd5b,0x3df83cf9,0x3cc8bdfb,0xbde23d71,0xbdac3dbe,0xbdfd3c96,
0xbd803d80,0xbda2bdc6,0xbde7bd5b,0xbcf9bdf8,0x3dd53d8e,0x3d153df5,0x3dac3dbe,0xbc963dfd,0xbd8ebdd5,0x3c49bdff,0xbd2cbdf1,0x3d84bddc,0x3cc83dfb,0xbd713de2,0xbbc93e00,0xbdce3d98,
0x3d803d80,0x3d713de2,0x3ddc3d84,0xbbc93e00,0xbcc83dfb,0x3da2bdc6,0x3c96bdfd,0x3df1bd2c,0x3dfbbcc8,0xbdf5bd15,0xbdf83cf9,0xbdacbdbe,0xbd8ebdd5,0x3c493dff,0x3d983dce,0xbd5b3de7,
0xbd803d80,0xbd15bdf5,0xbdcebd98,0x3d2cbdf1,0xbdfb3cc8,0xbdffbc49,0xbddc3d84,0xbdbebdac,0xbcc83dfb,0xbd713de2,0x3c963dfd,0xbde73d5b,0x3dd53d8e,0x3da23dc6,0x3df83cf9,0x3bc93e00,
0x3d803d80,0x3c493dff,0x3dbe3dac,0xbd983dce,0xbd8ebdd5,0x3d713de2,0x3df13d2c,0xbcf93df8,0xbdd5bd8e,0x3dc63da2,0x3e00bbc9,0x3c963dfd,0xbdfbbcc8,0x3df53d15,0x3de7bd5b,0x3d843ddc,
0xbd803d80,0x3c49bdff,0xbdacbdbe,0x3dcebd98,0x3d8ebdd5,0x3d71bde2,0xbd2cbdf1,0x3df8bcf9,0x3dd5bd8e,0x3dc6bda2,0x3bc9be00,0x3dfd3c96,0x3dfbbcc8,0x3df5bd15,0x3d5bbde7,0x3ddc3d84,
0x3d803d80,0xbd153df5,0x3d983dce,0xbdf13d2c,0x3dfb3cc8,0xbdff3c49,0xbd843ddc,0xbdacbdbe,0x3cc83dfb,0xbd71bde2,0xbdfdbc96,0x3d5bbde7,0xbdd53d8e,0x3da2bdc6,0xbcf9bdf8,0x3e003bc9,
0xbd803d80,0x3d71bde2,0xbd84bddc,0x3e00bbc9,0x3cc83dfb,0x3da23dc6,0x3dfdbc96,0xbd2c3df1,0xbdfbbcc8,0xbdf53d15,0xbcf93df8,0xbdbebdac,0x3d8ebdd5,0x3c49bdff,0xbdcebd98,0x3de7bd5b,
0x3d803d80,0xbda23dc6,0x3d5b3de7,0xbdf8bcf9,0xbdd53d8e,0x3d15bdf5,0xbdbebdac,0x3dfdbc96,0x3d8ebdd5,0x3c493dff,0x3df13d2c,0xbddc3d84,0xbcc83dfb,0xbd71bde2,0xbe003bc9,0x3d98bdce,
0xbd803d80,0x3dc6bda2,0xbd2cbdf1,0x3ddc3d84,0xbdd5bd8e,0xbdf53d15,0xbbc93e00,0xbd98bdce,0x3d8e3dd5,0x3dff3c49,0x3d5bbde7,0x3cf93df8,0xbcc8bdfb,0xbde2bd71,0xbdbe3dac,0x3c96bdfd,
0x3d803d80,0xbde23d71,0x3cf93df8,0xbdacbdbe,0x3cc8bdfb,0x3dc63da2,0x3dcebd98,0xbd5b3de7,0xbdfb3cc8,0x3d15bdf5,0xbddcbd84,0x3e003bc9,0x3d8e3dd5,0xbdff3c49,0xbc963dfd,0xbd2cbdf1,
0xbd803d80,0x3df5bd15,0xbc96bdfd,0x3d5b3de7,0x3dfbbcc8,0x3c49bdff,0xbdf8bcf9,0x3e00bbc9,0x3cc8bdfb,0xbde2bd71,0xbd983dce,0x3d2cbdf1,0xbdd5bd8e,0xbdc63da2,0x3d843ddc,0xbdbebdac,
0x3d803d80,0xbdff3c49,0x3bc93e00,0xbc96bdfd,0x3d8e3dd5,0xbde23d71,0x3d5b3de7,0xbd84bddc,0x3dd53d8e,0xbda23dc6,0x3dbe3dac,0xbdcebd98,0x3dfb3cc8,0xbd153df5,0x3df13d2c,0xbdf8bcf9,
0xbd803d80,0x3dff3c49,0x3bc9be00,0xbc963dfd,0xbd8e3dd5,0x3de23d71,0x3d5bbde7,0xbd843ddc,0xbdd53d8e,0x3da23dc6,0x3dbebdac,0xbdce3d98,0xbdfb3cc8,0x3d153df5,0x3df1bd2c,0xbdf83cf9,
0x3d803d80,0xbdf5bd15,0xbc963dfd,0x3d5bbde7,0xbdfbbcc8,0xbc49bdff,0xbdf83cf9,0x3e003bc9,0xbcc8bdfb,0x3de2bd71,0xbd98bdce,0x3d2c3df1,0x3dd5bd8e,0x3dc63da2,0x3d84bddc,0xbdbe3dac,
0xbd803d80,0x3de23d71,0x3cf9bdf8,0xbdac3dbe,0xbcc8bdfb,0xbdc63da2,0x3dce3d98,0xbd5bbde7,0x3dfb3cc8,0xbd15bdf5,0xbddc3d84,0x3e00bbc9,0xbd8e3dd5,0x3dff3c49,0xbc96bdfd,0xbd2c3df1,
0x3d803d80,0xbdc6bda2,0xbd2c3df1,0x3ddcbd84,0x3dd5bd8e,0x3df53d15,0xbbc9be00,0xbd983dce,0xbd8e3dd5,0xbdff3c49,0x3d5b3de7,0x3cf9bdf8,0x3cc8bdfb,0x3de2bd71,0xbdbebdac,0x3c963dfd,
0xbd803d80,0x3da23dc6,0x3d5bbde7,0xbdf83cf9,0x3dd53d8e,0xbd15bdf5,0xbdbe3dac,0x3dfd3c96,0xbd8ebdd5,0xbc493dff,0x3df1bd2c,0xbddcbd84,0x3cc83dfb,0x3d71bde2,0xbe00bbc9,0x3d983dce,
0x3d803d80,0xbd71bde2,0xbd843ddc,0x3e003bc9,0xbcc83dfb,0xbda23dc6,0x3dfd3c96,0xbd2cbdf1,0x3dfbbcc8,0x3df53d15,0xbcf9bdf8,0xbdbe3dac,0xbd8ebdd5,0xbc49bdff,0xbdce3d98,0x3de73d5b,
0xbd803d80,0x3d153df5,0x3d98bdce,0xbdf1bd2c,0xbdfb3cc8,0x3dff3c49,0xbd84bddc,0xbdac3dbe,0xbcc83dfb,0x3d71bde2,0xbdfd3c96,0x3d5b3de7,0x3dd53d8e,0xbda2bdc6,0xbcf93df8,0x3e00bbc9,
0x3d803d80,0xbc49bdff,0xbdac3dbe,0x3dce3d98,0xbd8ebdd5,0xbd71bde2,0xbd2c3df1,0x3df83cf9,0xbdd5bd8e,0xbdc6bda2,0x3bc93e00,0x3dfdbc96,0xbdfbbcc8,0xbdf5bd15,0x3d5b3de7,0x3ddcbd84,
0xbd803d80,0xbc493dff,0x3dbebdac,0xbd98bdce,0x3d8ebdd5,0xbd713de2,0x3df1bd2c,0xbcf9bdf8,0x3dd5bd8e,0xbdc63da2,0x3e003bc9,0x3c96bdfd,0x3dfbbcc8,0xbdf53d15,0x3de73d5b,0x3d84bddc,
0x3d803d80,0x3d15bdf5,0xbdce3d98,0x3d2c3df1,0x3dfb3cc8,0x3dffbc49,0xbddcbd84,0xbdbe3dac,0x3cc83dfb,0x3d713de2,0x3c96bdfd,0xbde7bd5b,0xbdd53d8e,0xbda23dc6,0x3df8bcf9,0x3bc9be00,
0xbd803d80,0xbd713de2,0x3ddcbd84,0xbbc9be00,0x3cc83dfb,0xbda2bdc6,0x3c963dfd,0x3df13d2c,0xbdfbbcc8,0x3df5bd15,0xbdf8bcf9,0xbdac3dbe,0x3d8ebdd5,0xbc493dff,0x3d98bdce,0xbd5bbde7,
0x3d803d80,0x3da2bdc6,0xbde73d5b,0xbcf93df8,0xbdd53d8e,0xbd153df5,0x3dacbdbe,0xbc96bdfd,0x3d8ebdd5,0xbc49bdff,0xbd2c3df1,0x3d843ddc,0xbcc83dfb,0x3d713de2,0xbbc9be00,0xbdcebd98,
0xbd803d80,0xbdc63da2,0x3df1bd2c,0x3d84bddc,0xbdd5bd8e,0x3df5bd15,0xbe00bbc9,0xbdce3d98,0x3d8e3dd5,0xbdffbc49,0x3de73d5b,0x3df8bcf9,0xbcc8bdfb,0x3de23d71,0xbdacbdbe,0xbdfdbc96,
0x3d803d80,0x3de2bd71,0xbdf83cf9,0xbdbe3dac,0x3cc8bdfb,0xbdc6bda2,0x3d983dce,0x3de73d5b,0xbdfb3cc8,0xbd153df5,0x3d84bddc,0x3bc9be00,0x3d8e3dd5,0x3dffbc49,0xbdfdbc96,0xbdf13d2c,
0xbd803d80,0xbdf53d15,0x3dfdbc96,0x3de7bd5b,0x3dfbbcc8,0xbc493dff,0x3cf9bdf8,0xbbc9be00,0x3cc8bdfb,0x3de23d71,0xbdcebd98,0xbdf1bd2c,0xbdd5bd8e,0x3dc6bda2,0xbddc3d84,0xbdac3dbe,
0x3d803d80,0x3dffbc49,0xbe003bc9,0xbdfd3c96,0x3d8e3dd5,0x3de2bd71,0xbde73d5b,0xbddc3d84,0x3dd53d8e,0x3da2bdc6,0xbdac3dbe,0xbd983dce,0x3dfb3cc8,0x3d15bdf5,0xbd2c3df1,0xbcf93df8,
0xbd153df5,0xbc963dfd,0xbc173dff,0xbce03dfa,0xbd8e3dd5,0xbdac3dbe,0xbd9d3dca,0xbdb93db1,0xbded3d44,0xbdf83cf9,0xbdf33d21,0xbdfc3caf,0xbdfbbcc8,0xbdf1bd2c,0xbdf7bd09,0xbdeabd4f,
0xbda23dc6,0xbd2c3df1,0xbcaf3dfc,0xbd7c3ddf,0xbdfb3cc8,0xbdfdbc96,0xbe003b49,0xbdf3bd21,0xbd44bded,0xbbc9be00,0xbce0bdfa,0x3c7bbdfe,0x3dd5bd8e,0x3df8bcf9,0x3deabd4f,0x3dffbc17,
0xbde23d71,0xbd843ddc,0xbd093df7,0xbdb93db1,0xbdd5bd8e,0xbd5bbde7,0xbda7bdc2,0xbcafbdfc,0x3dedbd44,0x3dfd3c96,0x3dfebc7b,0x3dea3d4f,0xbcc83dfb,0xbdac3dbe,0xbd663de5,0xbdd83d89,
0xbdff3c49,0xbdac3dbe,0xbd383def,0xbde53d66,0xbcc8bdfb,0x3d84bddc,0x3cafbdfc,0x3dcabd9d,0x3d443ded,0xbd2c3df1,0x3b493e00,0xbda73dc2,0xbd8ebdd5,0x3c96bdfd,0xbce0bdfa,0x3d7cbddf,
0xbdf5bd15,0xbdce3d98,0xbd663de5,0xbdfc3caf,0x3d8ebdd5,0x3e00bbc9,0x3ddfbd7c,0x3dea3d4f,0xbded3d44,0xbddcbd84,0xbdffbc17,0xbd89bdd8,0x3dfb3cc8,0x3d5b3de7,0x3dca3d9d,0xbb493e00,
0xbdc6bda2,0xbde73d5b,0xbd893dd8,0xbdfebc7b,0x3dfbbcc8,0x3d983dce,0x3def3d38,0x3c173dff,0xbd44bded,0x3dacbdbe,0x3cafbdfc,0x3df7bd09,0xbdd53d8e,0xbddcbd84,0xbe003b49,0xbd66bde5,
0xbd71bde2,0xbdf83cf9,0xbd9d3dca,0xbdeabd4f,0x3dd53d8e,0xbd2c3df1,0x3d213df3,0xbdd83d89,0x3dedbd44,0x3d983dce,0x3df73d09,0xbb493e00,0x3cc8bdfb,0x3e00bbc9,0x3dc2bda7,0x3dd13d93,
0xbc49bdff,0xbe003bc9,0xbdb13db9,0xbdc2bda7,0x3cc83dfb,0xbdf83cf9,0xbd893dd8,0xbddfbd7c,0x3d443ded,0xbde73d5b,0xbd383def,0xbdf3bd21,0x3d8e3dd5,0xbdce3d98,0xbcaf3dfc,0xbdfebc7b,
0x3d15bdf5,0xbdfdbc96,0xbdc23da7,0xbd89bdd8,0xbd8e3dd5,0xbdbebdac,0xbdfe3c7b,0x3b49be00,0xbded3d44,0xbcf9bdf8,0xbde5bd66,0x3d93bdd1,0xbdfbbcc8,0x3d2cbdf1,0xbd7cbddf,0x3defbd38,
0x3da2bdc6,0xbdf1bd2c,0xbdd13d93,0xbd09bdf7,0xbdfb3cc8,0x3c96bdfd,0xbdb9bdb1,0x3de5bd66,0xbd44bded,0x3e00bbc9,0x3d89bdd8,0x3d9d3dca,0x3dd5bd8e,0x3cf93df8,0x3def3d38,0xbda73dc2,
0x3de2bd71,0xbddcbd84,0xbddf3d7c,0x3b49be00,0xbdd5bd8e,0x3de7bd5b,0x3c17bdff,0x3dd13d93,0x3dedbd44,0xbc963dfd,0x3dca3d9d,0xbdef3d38,0xbcc83dfb,0xbdbebdac,0xbdf33d21,0x3ce0bdfa,
0x3dffbc49,0xbdbebdac,0xbdea3d4f,0x3d21bdf3,0xbcc8bdfb,0x3ddc3d84,0x3dd1bd93,0xbc7b3dfe,0x3d443ded,0xbdf1bd2c,0xbdb13db9,0xbc17bdff,0xbd8ebdd5,0x3dfd3c96,0x3d89bdd8,0x3d093df7,
0x3df53d15,0xbd98bdce,0xbdf33d21,0x3d93bdd1,0x3d8ebdd5,0x3bc93e00,0x3df73d09,0xbdef3d38,0xbded3d44,0x3d84bddc,0xbda7bdc2,0x3dfa3ce0,0x3dfb3cc8,0xbde73d5b,0x3c7b3dfe,0xbdb1bdb9,
0x3dc63da2,0xbd5bbde7,0xbdfa3ce0,0x3dcabd9d,0x3dfbbcc8,0xbdce3d98,0x3d4f3dea,0xbdc2bda7,0xbd44bded,0x3dbe3dac,0x3dd1bd93,0xbd7c3ddf,0xbdd53d8e,0x3d84bddc,0xbdb9bdb1,0x3df33d21,
0x3d713de2,0xbcf9bdf8,0xbdfe3c7b,0x3defbd38,0x3dd53d8e,0xbdf1bd2c,0xbd663de5,0x3ce0bdfa,0x3dedbd44,0xbdce3d98,0x3d7c3ddf,0xbdb1bdb9,0x3cc8bdfb,0x3bc93e00,0x3dff3c17,0xbdfc3caf,
0x3c493dff,0xbbc9be00,0xbe003b49,0x3dffbc17,0x3cc83dfb,0xbcf9bdf8,0xbdfa3ce0,0x3df7bd09,0x3d443ded,0xbd5bbde7,0xbdea3d4f,0x3de5bd66,0x3d8e3dd5,0xbd98bdce,0xbdd13d93,0x3dcabd9d,
0xbd153df5,0x3c96bdfd,0xbdffbc17,0x3dfa3ce0,0xbd8e3dd5,0x3dacbdbe,0xbdcabd9d,0x3db13db9,0xbded3d44,0x3df8bcf9,0xbd21bdf3,0x3caf3dfc,0xbdfbbcc8,0x3df13d2c,0x3d09bdf7,0xbd4f3dea,
0xbda23dc6,0x3d2cbdf1,0xbdfcbcaf,0x3ddf3d7c,0xbdfb3cc8,0x3dfd3c96,0xbb49be00,0xbd213df3,0xbd44bded,0x3bc93e00,0x3dfabce0,0xbdfebc7b,0x3dd5bd8e,0xbdf83cf9,0x3d4f3dea,0xbc17bdff,
0xbde23d71,0x3d84bddc,0xbdf7bd09,0x3db13db9,0xbdd5bd8e,0x3d5b3de7,0x3dc2bda7,0xbdfc3caf,0x3dedbd44,0xbdfdbc96,0x3c7b3dfe,0x3d4fbdea,0xbcc83dfb,0x3dacbdbe,0xbde5bd66,0x3d893dd8,
0xbdff3c49,0x3dacbdbe,0xbdefbd38,0x3d663de5,0xbcc8bdfb,0xbd843ddc,0x3dfc3caf,0xbd9dbdca,0x3d443ded,0x3d2cbdf1,0xbe003b49,0x3dc23da7,0xbd8ebdd5,0xbc963dfd,0x3dfabce0,0xbddfbd7c,
0xbdf5bd15,0x3dcebd98,0xbde5bd66,0x3caf3dfc,0x3d8ebdd5,0xbe003bc9,0x3d7c3ddf,0x3d4fbdea,0xbded3d44,0x3ddc3d84,0x3c17bdff,0xbdd83d89,0x3dfb3cc8,0xbd5bbde7,0xbd9d3dca,0x3e003b49,
0xbdc6bda2,0x3de7bd5b,0xbdd8bd89,0xbc7b3dfe,0x3dfbbcc8,0xbd98bdce,0xbd383def,0x3dffbc17,0xbd44bded,0xbdac3dbe,0x3dfc3caf,0xbd09bdf7,0xbdd53d8e,0x3ddc3d84,0xbb49be00,0xbde53d66,
0xbd71bde2,0x3df8bcf9,0xbdcabd9d,0xbd4f3dea,0x3dd53d8e,0x3d2cbdf1,0xbdf33d21,0x3d893dd8,0x3dedbd44,0xbd98bdce,0xbd093df7,0x3e003b49,0x3cc8bdfb,0xbe003bc9,0x3da73dc2,0x3d93bdd1,
0xbc49bdff,0x3e00bbc9,0xbdb9bdb1,0xbda73dc2,0x3cc83dfb,0x3df8bcf9,0xbdd8bd89,0xbd7c3ddf,0x3d443ded,0x3de7bd5b,0xbdefbd38,0xbd213df3,0x3d8e3dd5,0x3dcebd98,0xbdfcbcaf,0xbc7b3dfe,
0x3d15bdf5,0x3dfd3c96,0xbda7bdc2,0xbdd83d89,0xbd8e3dd5,0x3dbe3dac,0xbc7bbdfe,0xbe00bb49,0xbded3d44,0x3cf93df8,0x3d66bde5,0xbdd1bd93,0xbdfbbcc8,0xbd2c3df1,0x3ddfbd7c,0xbd38bdef,
0x3da2bdc6,0x3df13d2c,0xbd93bdd1,0xbdf73d09,0xbdfb3cc8,0xbc963dfd,0x3db1bdb9,0xbd66bde5,0xbd44bded,0xbe003bc9,0x3dd83d89,0x3dcabd9d,0x3dd5bd8e,0xbcf9bdf8,0xbd383def,0x3dc23da7,
0x3de2bd71,0x3ddc3d84,0xbd7cbddf,0xbe00bb49,0xbdd5bd8e,0xbde73d5b,0x3dff3c17,0x3d93bdd1,0x3dedbd44,0x3c96bdfd,0xbd9d3dca,0x3d383def,0xbcc83dfb,0x3dbe3dac,0xbd21bdf3,0xbdfabce0,
0x3dffbc49,0x3dbe3dac,0xbd4fbdea,0xbdf3bd21,0xbcc8bdfb,0xbddcbd84,0x3d933dd1,0x3dfe3c7b,0x3d443ded,0x3df13d2c,0xbdb9bdb1,0xbdff3c17,0xbd8ebdd5,0xbdfdbc96,0x3dd83d89,0x3df7bd09,
0x3df53d15,0x3d983dce,0xbd21bdf3,0xbdd1bd93,0x3d8ebdd5,0xbbc9be00,0xbd093df7,0x3d383def,0xbded3d44,0xbd843ddc,0x3dc2bda7,0x3ce0bdfa,0x3dfb3cc8,0x3de7bd5b,0xbdfe3c7b,0xbdb93db1,
0x3dc63da2,0x3d5b3de7,0xbce0bdfa,0xbd9dbdca,0x3dfbbcc8,0x3dcebd98,0xbdea3d4f,0xbda73dc2,0xbd44bded,0xbdbebdac,0x3d933dd1,0x3ddf3d7c,0xbdd53d8e,0xbd843ddc,0x3db1bdb9,0x3d21bdf3,
0x3d713de2,0x3cf93df8,0xbc7bbdfe,0xbd38bdef,0x3dd53d8e,0x3df13d2c,0xbde5bd66,0xbdfabce0,0x3dedbd44,0x3dcebd98,0xbddf3d7c,0xbdb93db1,0x3cc8bdfb,0xbbc9be00,0xbc173dff,0x3caf3dfc,
0x3c493dff,0x3bc93e00,0xbb49be00,0xbc17bdff,0x3cc83dfb,0x3cf93df8,0xbce0bdfa,0xbd09bdf7,0x3d443ded,0x3d5b3de7,0xbd4fbdea,0xbd66bde5,0x3d8e3dd5,0x3d983dce,0xbd93bdd1,0xbd9dbdca,
0xbdb53d80,0xbd98bdce,0xbda7bdc2,0xbd89bdd8,0xbdc63da2,0xbbc9be00,0xbc7bbdfe,0x3b49be00,0xbdff3c49,0x3d84bddc,0x3d66bde5,0x3d93bdd1,0xbde2bd71,0x3de7bd5b,0x3ddfbd7c,0x3defbd38,
0x3db53d80,0x3d5b3de7,0x3d933dd1,0x3d093df7,0xbde2bd71,0xbdce3d98,0xbdb13db9,0xbde53d66,0x3d15bdf5,0xbdbebdac,0xbdd8bd89,0xbd9dbdca,0x3dff3c49,0x3d84bddc,0x3d38bdef,0x3da7bdc2,
0xbdb53d80,0xbcf9bdf8,0xbd7cbddf,0x3b49be00,0x3c49bdff,0x3df13d2c,0x3dff3c17,0x3dd13d93,0x3dc63da2,0xbdce3d98,0xbd9d3dca,0xbdef3d38,0xbdf53d15,0xbbc9be00,0xbd21bdf3,0x3ce0bdfa,
0x3db53d80,0x3bc93e00,0x3d4f3dea,0xbd213df3,0x3df5bd15,0xbcf9bdf8,0xbd93bdd1,0x3c7bbdfe,0xbde23d71,0x3d5b3de7,0x3db93db1,0x3c173dff,0x3dc6bda2,0xbd98bdce,0xbdd8bd89,0xbd09bdf7,
0xbdb53d80,0x3c96bdfd,0xbd21bdf3,0x3d93bdd1,0x3da23dc6,0xbdac3dbe,0xbd093df7,0xbdef3d38,0xbc49bdff,0x3df8bcf9,0x3dc2bda7,0x3dfa3ce0,0xbd713de2,0xbdf1bd2c,0xbdfe3c7b,0xbdb1bdb9,
0x3db53d80,0xbd2c3df1,0x3ce03dfa,0xbdca3d9d,0xbd713de2,0x3dfd3c96,0x3deabd4f,0x3dc23da7,0x3df53d15,0xbbc9be00,0xbd93bdd1,0x3d7cbddf,0x3c49bdff,0xbdf83cf9,0xbdb13db9,0xbdf3bd21,
0xbdb53d80,0x3d84bddc,0xbc7bbdfe,0x3defbd38,0xbdffbc49,0xbd5bbde7,0xbde5bd66,0x3ce0bdfa,0xbda23dc6,0xbdfdbc96,0xbddf3d7c,0xbdb1bdb9,0x3d153df5,0xbdac3dbe,0xbc173dff,0xbdfc3caf,
0x3db53d80,0xbdac3dbe,0x3b493e00,0xbdff3c17,0xbd15bdf5,0xbd843ddc,0x3ce03dfa,0xbdf73d09,0xbd71bde2,0xbd2c3df1,0x3d4f3dea,0xbde53d66,0xbda2bdc6,0xbc963dfd,0x3d933dd1,0xbdca3d9d,
0xbdb53d80,0x3dcebd98,0x3c17bdff,0x3dfa3ce0,0x3dc6bda2,0x3e00bbc9,0x3d9dbdca,0x3db13db9,0x3dffbc49,0x3ddc3d84,0x3df3bd21,0x3caf3dfc,0x3de23d71,0x3d5b3de7,0x3df73d09,0xbd4f3dea,
0x3db53d80,0xbde73d5b,0xbcaf3dfc,0xbddfbd7c,0x3de23d71,0xbd98bdce,0xbe003b49,0x3d21bdf3,0xbd153df5,0x3dacbdbe,0xbce0bdfa,0x3dfe3c7b,0xbdffbc49,0x3ddc3d84,0x3deabd4f,0x3c173dff,
0xbdb53d80,0x3df8bcf9,0x3d09bdf7,0x3db13db9,0xbc493dff,0xbd2c3df1,0x3da73dc2,0xbdfc3caf,0xbdc6bda2,0xbd98bdce,0xbdfe3c7b,0x3d4fbdea,0x3df5bd15,0x3e00bbc9,0x3d66bde5,0x3d893dd8,
0x3db53d80,0xbe003bc9,0xbd383def,0xbd66bde5,0xbdf53d15,0x3df8bcf9,0x3cafbdfc,0x3d9d3dca,0x3de2bd71,0xbde73d5b,0x3b493e00,0xbdc2bda7,0xbdc63da2,0x3dcebd98,0xbce0bdfa,0x3ddf3d7c,
0xbdb53d80,0x3dfd3c96,0x3d66bde5,0x3caf3dfc,0xbda2bdc6,0xbdbebdac,0xbddf3d7c,0x3d4fbdea,0x3c493dff,0x3cf93df8,0x3dff3c17,0xbdd83d89,0x3d71bde2,0x3d2cbdf1,0xbdcabd9d,0x3e003b49,
0x3db53d80,0xbdf1bd2c,0xbd893dd8,0x3c7bbdfe,0x3d71bde2,0xbc963dfd,0x3def3d38,0xbdff3c17,0xbdf5bd15,0x3e00bbc9,0x3cafbdfc,0x3d093df7,0xbc493dff,0xbcf9bdf8,0xbe003b49,0x3de5bd66,
0xbdb53d80,0x3ddc3d84,0x3d9dbdca,0xbd4f3dea,0x3dff3c49,0x3de7bd5b,0xbd21bdf3,0x3d893dd8,0x3da2bdc6,0x3c96bdfd,0xbdf7bd09,0x3e003b49,0xbd15bdf5,0xbdbebdac,0xbdc23da7,0x3d93bdd1,
0x3db53d80,0xbdbebdac,0xbdb13db9,0x3da7bdc2,0x3d153df5,0xbddcbd84,0xbd893dd8,0x3d7cbddf,0x3d713de2,0xbdf1bd2c,0xbd383def,0x3d21bdf3,0x3da23dc6,0xbdfdbc96,0xbcaf3dfc,0x3c7bbdfe,
0xbdb53d80,0x3d983dce,0x3dc2bda7,0xbdd83d89,0xbdc63da2,0x3bc93e00,0x3dfebc7b,0xbe00bb49,0xbdff3c49,0xbd843ddc,0x3de53d66,0xbdd1bd93,0xbde2bd71,0xbde73d5b,0x3d7c3ddf,0xbd38bdef,
0x3db53d80,0xbd5bbde7,0xbdd13d93,0x3df7bd09,0xbde2bd71,0x3dcebd98,0xbdb9bdb1,0x3d663de5,0x3d15bdf5,0x3dbe3dac,0x3d89bdd8,0xbdca3d9d,0x3dff3c49,0xbd843ddc,0x3def3d38,0xbdc2bda7,
0xbdb53d80,0x3cf93df8,0x3ddfbd7c,0xbe00bb49,0x3c49bdff,0xbdf1bd2c,0xbc173dff,0x3d93bdd1,0x3dc63da2,0x3dcebd98,0xbdcabd9d,0x3d383def,0xbdf53d15,0x3bc93e00,0x3df3bd21,0xbdfabce0,
0x3db53d80,0xbbc9be00,0xbdea3d4f,0x3df33d21,0x3df5bd15,0x3cf93df8,0x3dd1bd93,0xbdfebc7b,0xbde23d71,0xbd5bbde7,0xbdb13db9,0x3dffbc17,0x3dc6bda2,0x3d983dce,0x3d89bdd8,0xbdf73d09,
0xbdb53d80,0xbc963dfd,0x3df3bd21,0xbdd1bd93,0x3da23dc6,0x3dacbdbe,0xbdf7bd09,0x3d383def,0xbc49bdff,0xbdf83cf9,0x3da73dc2,0x3ce0bdfa,0xbd713de2,0x3df13d2c,0xbc7bbdfe,0xbdb93db1,
0x3db53d80,0x3d2cbdf1,0xbdfa3ce0,0x3d9d3dca,0xbd713de2,0xbdfdbc96,0x3d4f3dea,0x3da7bdc2,0x3df53d15,0x3bc93e00,0x3dd1bd93,0xbddfbd7c,0x3c49bdff,0x3df8bcf9,0xbdb9bdb1,0xbd213df3,
0xbdb53d80,0xbd843ddc,0x3dfebc7b,0xbd38bdef,0xbdffbc49,0x3d5b3de7,0x3d66bde5,0xbdfabce0,0xbda23dc6,0x3dfd3c96,0xbd7cbddf,0xbdb93db1,0x3d153df5,0x3dacbdbe,0xbdffbc17,0x3caf3dfc,
0x3db53d80,0x3dacbdbe,0xbe003b49,0x3c173dff,0xbd15bdf5,0x3d84bddc,0xbdfa3ce0,0x3d093df7,0xbd71bde2,0x3d2cbdf1,0xbdea3d4f,0x3d663de5,0xbda2bdc6,0x3c96bdfd,0xbdd13d93,0x3d9d3dca,
0xbdb53d80,0xbdce3d98,0x3dff3c17,0x3ce0bdfa,0x3dc6bda2,0xbe003bc9,0x3dca3d9d,0x3db9bdb1,0x3dffbc49,0xbddcbd84,0x3d213df3,0x3dfcbcaf,0x3de23d71,0xbd5bbde7,0xbd093df7,0x3dea3d4f,
0x3db53d80,0x3de7bd5b,0xbdfcbcaf,0xbd7c3ddf,0x3de23d71,0x3d983dce,0xbb49be00,0xbdf3bd21,0xbd153df5,0xbdac3dbe,0x3dfabce0,0x3c7bbdfe,0xbdffbc49,0xbddcbd84,0x3d4f3dea,0x3dffbc17,
0xbdb53d80,0xbdf83cf9,0x3df73d09,0x3db9bdb1,0xbc493dff,0x3d2cbdf1,0xbdc23da7,0x3caf3dfc,0xbdc6bda2,0x3d983dce,0xbc7bbdfe,0xbdeabd4f,0x3df5bd15,0xbe003bc9,0x3de53d66,0x3dd8bd89,
0x3db53d80,0x3e00bbc9,0xbdefbd38,0xbde53d66,0xbdf53d15,0xbdf83cf9,0x3dfc3caf,0x3dcabd9d,0x3de2bd71,0x3de7bd5b,0xbe003b49,0xbda73dc2,0xbdc63da2,0xbdce3d98,0x3dfabce0,0x3d7cbddf,
0xbdb53d80,0xbdfdbc96,0x3de53d66,0x3dfcbcaf,0xbda2bdc6,0x3dbe3dac,0xbd7cbddf,0xbdeabd4f,0x3c493dff,0xbcf9bdf8,0xbc173dff,0x3d893dd8,0x3d71bde2,0xbd2c3df1,0x3d9dbdca,0x3b49be00,
0x3db53d80,0x3df13d2c,0xbdd8bd89,0xbdfebc7b,0x3d71bde2,0x3c96bdfd,0xbd383def,0x3c173dff,0xbdf5bd15,0xbe003bc9,0x3dfc3caf,0x3df7bd09,0xbc493dff,0x3cf93df8,0xbb49be00,0xbd66bde5,
0xbdb53d80,0xbddcbd84,0x3dca3d9d,0x3dea3d4f,0x3dff3c49,0xbde73d5b,0x3df3bd21,0x3dd8bd89,0x3da2bdc6,0xbc963dfd,0x3d09bdf7,0x3b49be00,0xbd15bdf5,0x3dbe3dac,0xbda7bdc2,0xbdd1bd93,
0x3db53d80,0x3dbe3dac,0xbdb9bdb1,0xbdc2bda7,0x3d153df5,0x3ddc3d84,0xbdd8bd89,0xbddfbd7c,0x3d713de2,0x3df13d2c,0xbdefbd38,0xbdf3bd21,0x3da23dc6,0x3dfd3c96,0xbdfcbcaf,0xbdfebc7b,
0x3f800000,0x0,0x3f800000,0x0,0x3f800000,0x0,0x3f800000,0x0,0x3f800000,0x0,0x3f800000,0x0,0x3f800000,0x0,0x3f800000,0x0,
0x3f800000,0x0,0x3f7ffb11,0xbc490e90,0x3f7fec43,0xbcc90ab0,0x3f7fd397,0xbd16c32c,0x3f7fb10f,0xbd48fb30,0x3f7f84ab,0xbd7b2b74,0x3f7f4e6d,0xbd96a905,0x3f7f0e58,0xbdafb680,
0x3f800000,0x0,0x3f7fec43,0xbcc90ab0,0x3f7fb10f,0xbd48fb30,0x3f7f4e6d,0xbd96a905,0x3f7ec46d,0xbdc8bd36,0x3f7e1324,0xbdfab273,0x3f7d3aac,0xbe164083,0x3f7c3b28,0xbe2f10a2,
0x3f800000,0x0,0x3f7fd397,0xbd16c32c,0x3f7f4e6d,0xbd96a905,0x3f7e70b0,0xbde1bc2e,0x3f7d3aac,0xbe164083,0x3f7baccd,0xbe3b6ecf,0x3f79c79d,0xbe605c13,0x3f778bc5,0xbe827dc0,
0x3f800000,0x0,0x3f7fb10f,0xbd48fb30,0x3f7ec46d,0xbdc8bd36,0x3f7d3aac,0xbe164083,0x3f7b14be,0xbe47c5c2,0x3f7853f8,0xbe78cfcc,0x3f74fa0b,0xbe94a031,0x3f710908,0xbeac7cd4,
0x3f800000,0x0,0x3f7f84ab,0xbd7b2b74,0x3f7e1324,0xbdfab273,0x3f7baccd,0xbe3b6ecf,0x3f7853f8,0xbe78cfcc,0x3f740bdd,0xbe9aa086,0x3f6ed89e,0xbeb8442a,0x3f68bf3c,0xbed53641,
0x3f800000,0x0,0x3f7f4e6d,0xbd96a905,0x3f7d3aac,0xbe164083,0x3f79c79d,0xbe605c13,0x3f74fa0b,0xbe94a031,0x3f6ed89e,0xbeb8442a,0x3f676bd8,0xbedae880,0x3f5ebe05,0xbefc5d27,
0x3f800000,0x0,0x3f7f0e58,0xbdafb680,0x3f7c3b28,0xbe2f10a2,0x3f778bc5,0xbe827dc0,0x3f710908,0xbeac7cd4,0x3f68bf3c,0xbed53641,0x3f5ebe05,0xbefc5d27,0x3f531849,0xbf10d3cd,
0x3f800000,0x0,0x3f7b14be,0xbe47c5c2,0x3f6c835e,0xbec3ef15,0x3f54db31,0xbf0e39da,0x3f3504f3,0xbf3504f3,0x3f0e39da,0xbf54db31,0x3ec3ef15,0xbf6c835e,0x3e47c5c2,0xbf7b14be,
0x3f800000,0x0,0x3f7a7302,0xbe541501,0x3f6a09a7,0xbecf7bca,0x3f4f7a1f,0xbf15f6d9,0x3f2beb4a,0xbf3daef9,0x3f00e7e4,0xbf5d2d53,0x3ea09ae5,0xbf731447,0x3de1bc2e,0xbf7e70b0,
0x3f800000,0x0,0x3f79c79d,0xbe605c13,0x3f676bd8,0xbedae880,0x3f49d112,0xbf1d7fd1,0x3f226799,0xbf45e403,0x3ee63375,0xbf64aa59,0x3e78cfcc,0xbf7853f8,0x3cc90ab0,0xbf7fec43,
0x3f800000,0x0,0x3f791298,0xbe6c9a7f,0x3f64aa59,0xbee63375,0x3f43e200,0xbf24d225,0x3f187fc0,0xbf4d9f02,0x3ec9b953,0xbf6b4b0c,0x3e2f10a2,0xbf7c3b28,0xbd7b2b74,0xbf7f84ab,
0x3f800000,0x0,0x3f7853f8,0xbe78cfcc,0x3f61c598,0xbef15aea,0x3f3daef9,0xbf2beb4a,0x3f0e39da,0xbf54db31,0x3eac7cd4,0xbf710908,0x3dc8bd36,0xbf7ec46d,0xbe164083,0xbf7d3aac,
0x3f800000,0x0,0x3f778bc5,0xbe827dc0,0x3f5ebe05,0xbefc5d27,0x3f373a23,0xbf32c8c9,0x3f039c3d,0xbf5b941a,0x3e8e9a22,0xbf75dec6,0x3cc90ab0,0xbf7fec43,0xbe6c9a7f,0xbf791298,
0x3f800000,0x0,0x3f76ba07,0xbe888e93,0x3f5b941a,0xbf039c3d,0x3f3085bb,0xbf396842,0x3ef15aea,0xbf61c598,0x3e605c13,0xbf79c79d,0xbd48fb30,0xbf7fb10f,0xbea09ae5,0xbf731447,
0x3f800000,0x0,0x3f75dec6,0xbe8e9a22,0x3f584853,0xbf08f59b,0x3f299415,0xbf3fc767,0x3edae880,0xbf676bd8,0x3e22abb6,0xbf7cbfc9,0xbdfab273,0xbf7e1324,0xbec9b953,0xbf6b4b0c,
0x3f800000,0x0,0x3f7ec46d,0xbdc8bd36,0x3f7b14be,0xbe47c5c2,0x3f74fa0b,0xbe94a031,0x3f6c835e,0xbec3ef15,0x3f61c598,0xbef15aea,0x3f54db31,0xbf0e39da,0x3f45e403,0xbf226799,
0x3f800000,0x0,0x3f6b4b0c,0xbec9b953,0x3f3085bb,0xbf396842,0x3eb263ef,0xbf6ff573,0xbd48fb30,0xbf7fb10f,0xbee0924f,0xbf660f88,0xbf41d870,0xbf273656,0xbf740bdd,0xbe9aa086,
0x3f800000,0x0,0x3f6a09a7,0xbecf7bca,0x3f2beb4a,0xbf3daef9,0x3ea09ae5,0xbf731447,0xbdc8bd36,0xbf7ec46d,0xbefc5d27,0xbf5ebe05,0xbf4d9f02,0xbf187fc0,0xbf79c79d,0xbe605c13,
0x3f800000,0x0,0x3f68bf3c,0xbed53641,0x3f273656,0xbf41d870,0x3e8e9a22,0xbf75dec6,0xbe164083,0xbf7d3aac,0xbf0b9a6b,0xbf5695e5,0xbf584853,0xbf08f59b,0xbf7dabcc,0xbe09cf86,
0x3f800000,0x0,0x3f676bd8,0xbedae880,0x3f226799,0xbf45e403,0x3e78cfcc,0xbf7853f8,0xbe47c5c2,0xbf7b14be,0xbf187fc0,0xbf4d9f02,0xbf61c598,0xbef15aea,0xbf7fb10f,0xbd48fb30,
0x3f800000,0x0,0x3f660f88,0xbee0924f,0x3f1d7fd1,0xbf49d112,0x3e541501,0xbf7a7302,0xbe78cfcc,0xbf7853f8,0xbf24d225,0xbf43e200,0xbf6a09a7,0xbecf7bca,0xbf7fd397,0x3d16c32c,
0x3f800000,0x0,0x3f64aa59,0xbee63375,0x3f187fc0,0xbf4d9f02,0x3e2f10a2,0xbf7c3b28,0xbe94a031,0xbf74fa0b,0xbf3085bb,0xbf396842,0xbf710908,0xbeac7cd4,0xbf7e1324,0x3dfab273,
0x3f800000,0x0,0x3f633c5a,0xbeebcbbb,0x3f13682a,0xbf514d3d,0x3e09cf86,0xbf7dabcc,0xbeac7cd4,0xbf710908,0xbf3b8f3b,0xbf2e3bde,0xbf76ba07,0xbe888e93,0xbf7a7302,0x3e541501,
0x3f800000,0x0,0x3f74fa0b,0xbe94a031,0x3f54db31,0xbf0e39da,0x3f226799,0xbf45e403,0x3ec3ef15,0xbf6c835e,0x3dc8bd36,0xbf7ec46d,0xbe47c5c2,0xbf7b14be,0xbef15aea,0xbf61c598,
0x3f800000,0x0,0x3f531849,0xbf10d3cd,0x3eb8442a,0xbf6ed89e,0xbe6c9a7f,0xbf791298,0xbf3daef9,0xbf2beb4a,0xbf7dabcc,0xbe09cf86,0xbf64aa59,0x3ee63375,0xbef6e0cb,0x3f604621,
0x3f800000,0x0,0x3f514d3d,0xbf13682a,0x3eac7cd4,0xbf710908,0xbe888e93,0xbf76ba07,0xbf45e403,0xbf226799,0xbf7f4e6d,0xbd96a905,0xbf5b941a,0x3f039c3d,0xbecf7bca,0x3f6a09a7,
0x3f800000,0x0,0x3f4f7a1f,0xbf15f6d9,0x3ea09ae5,0xbf731447,0xbe9aa086,0xbf740bdd,0xbf4d9f02,0xbf187fc0,0xbf7ffb11,0xbc490e90,0xbf514d3d,0x3f13682a,0xbea68f12,0x3f721352,
0x3f800000,0x0,0x3f4d9f02,0xbf187fc0,0x3e94a031,0xbf74fa0b,0xbeac7cd4,0xbf710908,0xbf54db31,0xbf0e39da,0xbf7fb10f,0x3d48fb30,0xbf45e403,0x3f226799,0xbe78cfcc,0x3f7853f8,
0x3f800000,0x0,0x3f4bbbf8,0xbf1b02c6,0x3e888e93,0xbf76ba07,0xbebe1d4a,0xbf6db293,0xbf5b941a,0xbf039c3d,0xbf7e70b0,0x3de1bc2e,0xbf396842,0x3f3085bb,0xbe22abb6,0x3f7cbfc9,
0x3f800000,0x0,0x3f49d112,0xbf1d7fd1,0x3e78cfcc,0xbf7853f8,0xbecf7bca,0xbf6a09a7,0xbf61c598,0xbef15aea,0xbf7c3b28,0x3e2f10a2,0xbf2beb4a,0x3f3daef9,0xbd96a905,0x3f7f4e6d,
0x3f800000,0x0,0x3f47de65,0xbf1ff6cb,0x3e605c13,0xbf79c79d,0xbee0924f,0xbf660f88,0xbf676bd8,0xbedae880,0xbf791298,0x3e6c9a7f,0xbf1d7fd1,0x3f49d112,0x3c490e90,0x3f7ffb11,
0x3f800000,0x0,0x3f800000,0x0,0x3f800000,0x0,0x3f800000,0x0,0x40000000,0x0,0x3f800000,0x0,0x3f800000,0x0,0x3f800000,0x0,
0x3f800000,0x0,0x3f7ffb11,0xbc490e90,0x3f7fec43,0xbcc90ab0,0x3f7fd397,0xbd16c32c,0x3fffb10f,0xbdc8fb30,0x3f7f84ab,0xbd7b2b74,0x3f7f4e6d,0xbd96a905,0x3f7f0e58,0xbdafb680,
0x3f800000,0x0,0x3f7fec43,0xbcc90ab0,0x3f7fb10f,0xbd48fb30,0x3f7f4e6d,0xbd96a905,0x3ffec46d,0xbe48bd36,0x3f7e1324,0xbdfab273,0x3f7d3aac,0xbe164083,0x3f7c3b28,0xbe2f10a2,
0x3f800000,0x0,0x3f7fd397,0xbd16c32c,0x3f7f4e6d,0xbd96a905,0x3f7e70b0,0xbde1bc2e,0x3ffd3aac,0xbe964083,0x3f7baccd,0xbe3b6ecf,0x3f79c79d,0xbe605c13,0x3f778bc5,0xbe827dc0,
0x3f800000,0x0,0x3f7fb10f,0xbd48fb30,0x3f7ec46d,0xbdc8bd36,0x3f7d3aac,0xbe164083,0x3ffb14be,0xbec7c5c2,0x3f7853f8,0xbe78cfcc,0x3f74fa0b,0xbe94a031,0x3f710908,0xbeac7cd4,
0x3f800000,0x0,0x3f7f84ab,0xbd7b2b74,0x3f7e1324,0xbdfab273,0x3f7baccd,0xbe3b6ecf,0x3ff853f8,0xbef8cfcc,0x3f740bdd,0xbe9aa086,0x3f6ed89e,0xbeb8442a,0x3f68bf3c,0xbed53641,
0x3f800000,0x0,0x3f7f4e6d,0xbd96a905,0x3f7d3aac,0xbe164083,0x3f79c79d,0xbe605c13,0x3ff4fa0b,0xbf14a031,0x3f6ed89e,0xbeb8442a,0x3f676bd8,0xbedae880,0x3f5ebe05,0xbefc5d27,
0x3f800000,0x0,0x3f7f0e58,0xbdafb680,0x3f7c3b28,0xbe2f10a2,0x3f778bc5,0xbe827dc0,0x3ff10908,0xbf2c7cd4,0x3f68bf3c,0xbed53641,0x3f5ebe05,0xbefc5d27,0x3f531849,0xbf10d3cd,
0x3f800000,0x0,0x3f7ec46d,0xbdc8bd36,0x3f7b14be,0xbe47c5c2,0x3f74fa0b,0xbe94a031,0x3fec835e,0xbf43ef15,0x3f61c598,0xbef15aea,0x3f54db31,0xbf0e39da,0x3f45e403,0xbf226799,
0x3f800000,0x0,0x3f7e70b0,0xbde1bc2e,0x3f79c79d,0xbe605c13,0x3f721352,0xbea68f12,0x3fe76bd8,0xbf5ae880,0x3f59f26a,0xbf064b82,0x3f49d112,0xbf1d7fd1,0x3f373a23,0xbf32c8c9,
0x3f800000,0x0,0x3f7e1324,0xbdfab273,0x3f7853f8,0xbe78cfcc,0x3f6ed89e,0xbeb8442a,0x3fe1c598,0xbf715aea,0x3f514d3d,0xbf13682a,0x3f3daef9,0xbf2beb4a,0x3f273656,0xbf41d870,
0x3f800000,0x0,0x3f7dabcc,0xbe09cf86,0x3f76ba07,0xbe888e93,0x3f6b4b0c,0xbec9b953,0x3fdb941a,0xbf839c3d,0x3f47de65,0xbf1ff6cb,0x3f3085bb,0xbf396842,0x3f15f6d9,0xbf4f7a1f,
0x3f800000,0x0,0x3f7d3aac,0xbe164083,0x3f74fa0b,0xbe94a031,0x3f676bd8,0xbedae880,0x3fd4db31,0xbf8e39da,0x3f3daef9,0xbf2beb4a,0x3f226799,0xbf45e403,0x3f039c3d,0xbf5b941a,
0x3f800000,0x0,0x3f7cbfc9,0xbe22abb6,0x3f731447,0xbea09ae5,0x3f633c5a,0xbeebcbbb,0x3fcd9f02,0xbf987fc0,0x3f32c8c9,0xbf373a23,0x3f13682a,0xbf514d3d,0x3ee0924f,0xbf660f88,
0x3f800000,0x0,0x3f7c3b28,0xbe2f10a2,0x3f710908,0xbeac7cd4,0x3f5ebe05,0xbefc5d27,0x3fc5e403,0xbfa26799,0x3f273656,0xbf41d870,0x3f039c3d,0xbf5b941a,0x3eb8442a,0xbf6ed89e,
0x3f800000,0x0,0x3f7baccd,0xbe3b6ecf,0x3f6ed89e,0xbeb8442a,0x3f59f26a,0xbf064b82,0x3fbdaef9,0xbfabeb4a,0x3f1b02c6,0xbf4bbbf8,0x3ee63375,0xbf64aa59,0x3e8e9a22,0xbf75dec6,
0x3f800000,0x0,0x3f7b14be,0xbe47c5c2,0x3f6c835e,0xbec3ef15,0x3f54db31,0xbf0e39da,0x3fb504f3,0xbfb504f3,0x3f0e39da,0xbf54db31,0x3ec3ef15,0xbf6c835e,0x3e47c5c2,0xbf7b14be,
0x3f800000,0x0,0x3f7a7302,0xbe541501,0x3f6a09a7,0xbecf7bca,0x3f4f7a1f,0xbf15f6d9,0x3fabeb4a,0xbfbdaef9,0x3f00e7e4,0xbf5d2d53,0x3ea09ae5,0xbf731447,0x3de1bc2e,0xbf7e70b0,
0x3f800000,0x0,0x3f79c79d,0xbe605c13,0x3f676bd8,0xbedae880,0x3f49d112,0xbf1d7fd1,0x3fa26799,0xbfc5e403,0x3ee63375,0xbf64aa59,0x3e78cfcc,0xbf7853f8,0x3cc90ab0,0xbf7fec43,
0x3f800000,0x0,0x3f791298,0xbe6c9a7f,0x3f64aa59,0xbee63375,0x3f43e200,0xbf24d225,0x3f987fc0,0xbfcd9f02,0x3ec9b953,0xbf6b4b0c,0x3e2f10a2,0xbf7c3b28,0xbd7b2b74,0xbf7f84ab,
0x3f800000,0x0,0x3f7853f8,0xbe78cfcc,0x3f61c598,0xbef15aea,0x3f3daef9,0xbf2beb4a,0x3f8e39da,0xbfd4db31,0x3eac7cd4,0xbf710908,0x3dc8bd36,0xbf7ec46d,0xbe164083,0xbf7d3aac,
0x3f800000,0x0,0x3f778bc5,0xbe827dc0,0x3f5ebe05,0xbefc5d27,0x3f373a23,0xbf32c8c9,0x3f839c3d,0xbfdb941a,0x3e8e9a22,0xbf75dec6,0x3cc90ab0,0xbf7fec43,0xbe6c9a7f,0xbf791298,
0x3f800000,0x0,0x3f76ba07,0xbe888e93,0x3f5b941a,0xbf039c3d,0x3f3085bb,0xbf396842,0x3f715aea,0xbfe1c598,0x3e605c13,0xbf79c79d,0xbd48fb30,0xbf7fb10f,0xbea09ae5,0xbf731447,
0x3f800000,0x0,0x3f75dec6,0xbe8e9a22,0x3f584853,0xbf08f59b,0x3f299415,0xbf3fc767,0x3f5ae880,0xbfe76bd8,0x3e22abb6,0xbf7cbfc9,0xbdfab273,0xbf7e1324,0xbec9b953,0xbf6b4b0c,
0x3f800000,0x0,0x3f74fa0b,0xbe94a031,0x3f54db31,0xbf0e39da,0x3f226799,0xbf45e403,0x3f43ef15,0xbfec835e,0x3dc8bd36,0xbf7ec46d,0xbe47c5c2,0xbf7b14be,0xbef15aea,0xbf61c598,
0x3f800000,0x0,0x3f740bdd,0xbe9aa086,0x3f514d3d,0xbf13682a,0x3f1b02c6,0xbf4bbbf8,0x3f2c7cd4,0xbff10908,0x3d16c32c,0xbf7fd397,0xbe888e93,0xbf76ba07,0xbf0b9a6b,0xbf5695e5,
0x3f800000,0x0,0x3f731447,0xbea09ae5,0x3f4d9f02,0xbf187fc0,0x3f13682a,0xbf514d3d,0x3f14a031,0xbff4fa0b,0xbcc90ab0,0xbf7fec43,0xbeac7cd4,0xbf710908,0xbf1d7fd1,0xbf49d112,
0x3f800000,0x0,0x3f721352,0xbea68f12,0x3f49d112,0xbf1d7fd1,0x3f0b9a6b,0xbf5695e5,0x3ef8cfcc,0xbff853f8,0xbdafb680,0xbf7f0e58,0xbecf7bca,0xbf6a09a7,0xbf2e3bde,0xbf3b8f3b,
0x3f800000,0x0,0x3f710908,0xbeac7cd4,0x3f45e403,0xbf226799,0x3f039c3d,0xbf5b941a,0x3ec7c5c2,0xbffb14be,0xbe164083,0xbf7d3aac,0xbef15aea,0xbf61c598,0xbf3daef9,0xbf2beb4a,
0x3f800000,0x0,0x3f6ff573,0xbeb263ef,0x3f41d870,0xbf273656,0x3ef6e0cb,0xbf604621,0x3e964083,0xbffd3aac,0xbe541501,0xbf7a7302,0xbf08f59b,0xbf584853,0xbf4bbbf8,0xbf1b02c6,
0x3f800000,0x0,0x3f6ed89e,0xbeb8442a,0x3f3daef9,0xbf2beb4a,0x3ee63375,0xbf64aa59,0x3e48bd36,0xbffec46d,0xbe888e93,0xbf76ba07,0xbf187fc0,0xbf4d9f02,0xbf584853,0xbf08f59b,
0x3f800000,0x0,0x3f6db293,0xbebe1d4a,0x3f396842,0xbf3085bb,0x3ed53641,0xbf68bf3c,0x3dc8fb30,0xbfffb10f,0xbea68f12,0xbf721352,0xbf273656,0xbf41d870,0xbf633c5a,0xbeebcbbb,
0x3f800000,0x0,0x3f7fffb1,0xbb490fc6,0x3f7ffec4,0xbbc90f88,0x3f7ffd39,0xbc16cb58,0x3ffffb11,0xbcc90e90,0x3f7ff84a,0xbc7b514b,0x3f7ff4e6,0xbc96c9b6,0x3f7ff0e3,0xbcafea69,
0x3f800000,0x0,0x3f7ff84a,0xbc7b514b,0x3f7fe129,0xbcfb49ba,0x3f7fba9e,0xbd3c6dd5,0x3fff84ab,0xbdfb2b74,0x3f7f3f54,0xbd9cecf9,0x3f7eea9d,0xbdbc3ac3,0x3f7e868b,0xbddb7d37,
0x3f800000,0x0,0x3f7fe705,0xbce22a7a,0x3f7f9c18,0xbd621469,0x3f7f1f49,0xbda973ba,0x3ffe70b0,0xbe61bc2e,0x3f7d906e,0xbe0cec4a,0x3f7c7eb0,0xbe28defc,0x3f7b3bab,0xbe44b0b9,
0x3f800000,0x0,0x3f7fcbe2,0xbd2351cb,0x3f7f2f9d,0xbda3308c,0x3f7e2b72,0xbdf475c0,0x3ffcbfc9,0xbea2abb6,0x3f7aed37,0xbe4ada4f,0x3f78b47b,0xbe72b651,0x3f76167a,0xbe8d17c0,
0x3f800000,0x0,0x3f7fa6e3,0xbd55880e,0x3f7e9bc9,0xbdd53db9,0x3f7cdf6c,0xbe1f917b,0x3ffa7302,0xbed41501,0x3f77583a,0xbe840270,0x3f73913f,0xbe9d9e78,0x3f6f20b0,0xbeb6ccc3,
0x3f800000,0x0,0x3f7f7808,0xbd83db0a,0x3f7de0b1,0xbe039502,0x3f7b3bab,0xbe44b0b9,0x3ff78bc5,0xbf027dc0,0x3f72d4eb,0xbea21887,0x3f6d1c1d,0xbec1071e,0x3f666771,0xbedf28a9,
0x3f800000,0x0,0x3f7f3f54,0xbd9cecf9,0x3f7cfe73,0xbe1c76de,0x3f7940c0,0xbe698bba,0x3ff40bdd,0xbf1aa086,0x3f6d67a1,0xbebf926f,0x3f655e0b,0xbee363fa,0x3f5bfb34,0xbf02ef9f,
0x3f800000,0x0,0x3f7efcc9,0xbdb5f8da,0x3f7bf531,0xbe354098,0x3f76ef5b,0xbe870ada,0x3feff573,0xbf3263ef,0x3f671599,0xbedc53c1,0x3f5c61c7,0xbf0242b1,0x3f4fefa8,0xbf1553b7,
0x3f800000,0x0,0x3f7eb069,0xbdcefdb7,0x3f7ac516,0xbe4dee60,0x3f74484b,0xbe9920fe,0x3feb4b0c,0xbf49b953,0x3f5fe4e9,0xbef840c8,0x3f5233c6,0xbf121eb0,0x3f425b89,0xbf269de3,
0x3f800000,0x0,0x3f7e5a38,0xbde7fa9a,0x3f796e4e,0xbe667c66,0x3f714c7a,0xbeab0201,0x3fe60f88,0xbf60924f,0x3f57dc7f,0xbf099f4e,0x3f46e22a,0xbf212ff9,0x3f33587a,0xbf36ad7f,
0x3f800000,0x0,0x3f7dfa38,0xbe007745,0x3f77f110,0xbe7ee6e1,0x3f6dfcf2,0xbebca7af,0x3fe04621,0xbf76e0cb,0x3f4f0417,0xbf16999f,0x3f3a7ca4,0xbf2f61a5,0x3f2302d3,0xbf456439,
0x3f800000,0x0,0x3f7d906e,0xbe0cec4a,0x3f764d97,0xbe8b9507,0x3f6a5ad9,0xbece0bea,0x3fd9f26a,0xbf864b82,0x3f456439,0xbf2302d3,0x3f2d1469,0xbf3ca003,0x3f11796b,0xbf52a649,
0x3f800000,0x0,0x3f7d1cdd,0xbe195be0,0x3f748422,0xbe97a117,0x3f666771,0xbedf28a9,0x3fd31849,0xbf90d3cd,0x3f3b0629,0xbf2ecef7,0x3f1ebc12,0xbf48d8b3,0x3efdbabb,0xbf5e5aa6,
0x3f800000,0x0,0x3f7c9f8a,0xbe25c58c,0x3f7294f8,0xbea395c5,0x3f62241a,0xbeeff7fb,0x3fcbbbf8,0xbf9b02c6,0x3f2ff3e6,0xbf39f2ac,0x3f0f8784,0xbf53fac3,0x3ed6a399,0xbf686b39,
0x3f800000,0x0,0x3f7c187a,0xbe3228d4,0x3f708066,0xbeaf713a,0x3f5d924d,0xbf003a06,0x3fc3e200,0xbfa4d225,0x3f24381a,0xbf446337,0x3eff17b2,0xbf5df6be,0x3eadf73c,0xbf70c501,
0x3f800000,0x0,0x3f7b87b2,0xbe3e853e,0x3f6e46be,0xbebb31a0,0x3f58b3a1,0xbf084b92,0x3fbb8f3b,0xbfae3bde,0x3f17de12,0xbf4e1689,0x3eddbe79,0xbf66becc,0x3e840270,0xbf77583a,
0x3f800000,0x0,0x3f7aed37,0xbe4ada4f,0x3f6be858,0xbec6d529,0x3f5389c7,0xbf102dd5,0x3fb2c8c9,0xbfb73a23,0x3f0af1b7,0xbf570348,0x3ebb31a0,0xbf6e46be,0x3e3228d4,0xbf7c187a,
0x3f800000,0x0,0x3f7a4910,0xbe57278f,0x3f696591,0xbed25a09,0x3f4e1689,0xbf17de12,0x3fa99415,0xbfbfc767,0x3efafef7,0xbf5f20db,0x3e97a117,0xbf748422,0x3db5f8da,0xbf7efcc9,
0x3f800000,0x0,0x3f799b43,0xbe636c83,0x3f66becc,0xbeddbe79,0x3f485bca,0xbf1f599f,0x3f9ff6cb,0xbfc7de65,0x3edf28a9,0xbf666771,0x3e667c66,0xbf796e4e,0x3b490fc6,0xbf7fffb1,
0x3f800000,0x0,0x3f78e3d6,0xbe6fa8b2,0x3f63f473,0xbee900b7,0x3f425b89,0xbf269de3,0x3f95f6d9,0xbfcf7a1f,0x3ec27b55,0xbf6cd007,0x3e1c76de,0xbf7cfe73,0xbda973ba,0xbf7f1f49,
0x3f800000,0x0,0x3f7822d1,0xbe7bdba4,0x3f6106f2,0xbef41f07,0x3f3c17d9,0xbf2da859,0x3f8b9a6b,0xbfd695e5,0x3ea5129f,0xbf725470,0x3da3308c,0xbf7f2f9d,0xbe2bf804,0xbf7c5d3a,
0x3f800000,0x0,0x3f77583a,0xbe840270,0x3f5df6be,0xbeff17b2,0x3f3592e7,0xbf34768f,0x3f80e7e4,0xbfdd2d53,0x3e870ada,0xbf76ef5b,0x3bc90f88,0xbf7ffec4,0xbe80f8c0,0xbf77beb7,
0x3f800000,0x0,0x3f76841b,0xbe8a11f7,0x3f5ac450,0xbf04f484,0x3f2ecef7,0xbf3b0629,0x3f6bcbbb,0xbfe33c5a,0x3e5101f1,0xbf7a9c59,0xbd8a200a,0xbf7f6ac7,0xbeab0201,0xbf714c7a,
0x3f800000,0x0,0x3f75a67b,0xbe901c2c,0x3f577026,0xbf0a48ad,0x3f27ce61,0xbf4154e1,0x3f553641,0xbfe8bf3c,0x3e1324ca,0xbf7d57de,0xbe1008b7,0xbf7d7474,0xbed3c867,0xbf6912ae,
0x3f800000,0x0,0x3f74bf62,0xbe9620d2,0x3f53fac3,0xbf0f8784,0x3f209393,0xbf476085,0x3f3e1d4a,0xbfedb293,0x3da973ba,0xbf7f1f49,0xbe5a3997,0xbf7a1e84,0xbefafef7,0xbf5f20db,
0x3f800000,0x0,0x3f73ced9,0xbe9c1faf,0x3f5064af,0xbf14b039,0x3f19210f,0xbf4d26fd,0x3f268f12,0xbff21352,0x3cafea69,0xbf7ff0e3,0xbe919ddd,0xbf756d97,0xbf102dd5,0xbf5389c7,
0x3f800000,0x0,0x3f72d4eb,0xbea21887,0x3f4cae79,0xbf19c200,0x3f11796b,0xbf52a649,0x3f0e9a22,0xbff5dec6,0xbd2351cb,0xbf7fcbe2,0xbeb554ec,0xbf6f6830,0xbf21cbfb,0xbf466354,
0x3f800000,0x0,0x3f71d19f,0xbea80b1f,0x3f48d8b3,0xbf1ebc12,0x3f099f4e,0xbf57dc7f,0x3eec9a7f,0xbff91298,0xbdcefdb7,0xbf7eb069,0xbed8106b,0xbf6816a8,0xbf3238aa,0xbf37c655,
0x3f800000,0x0,0x3f70c501,0xbeadf73c,0x3f44e3f5,0xbf239da9,0x3f019573,0xbf5cc7d1,0x3ebb6ecf,0xbffbaccd,0xbe25c58c,0xbf7c9f8a,0xbef9a02d,0xbf5f8327,0xbf4154e1,0xbf27ce61,
0x3f800000,0x0,0x3f6faf1b,0xbeb3dca5,0x3f40d0da,0xbf286605,0x3ef2bd43,0xbf61668a,0x3e89cf86,0xbffdabcc,0xbe636c83,0xbf799b43,0xbf0cead0,0xbf55b993,0xbf4f0417,0xbf16999f,
0x3f800000,0x0,0x3f6e8ff8,0xbeb9bb1e,0x3f3ca003,0xbf2d1469,0x3ee1fb6a,0xbf65b710,0x3e2fb680,0xbfff0e58,0xbe901c2c,0xbf75a67b,0xbf1c420c,0xbf4ac77f,0xbf5b2c79,0xbf044889,
0x3f800000,0x0,0x3f6d67a1,0xbebf926f,0x3f385216,0xbf31a81d,0x3ed0eb2a,0xbf69b7e4,0x3d96c32c,0xbfffd397,0xbeadf73c,0xbf70c501,0xbf2ac082,0xbf3ebc1b,0xbf65b710,0xbee1fb6a,
0x3f800000,0x0,0x3f7ffec4,0xbbc90f88,0x3f7ffb11,0xbc490e90,0x3f7ff4e6,0xbc96c9b6,0x3fffec43,0xbd490ab0,0x3f7fe129,0xbcfb49ba,0x3f7fd397,0xbd16c32c,0x3f7fc38f,0xbd2fe007,
0x3f800000,0x0,0x3f7ff4e6,0xbc96c9b6,0x3f7fd397,0xbd16c32c,0x3f7f9c18,0xbd621469,0x3fff4e6d,0xbe16a905,0x3f7eea9d,0xbdbc3ac3,0x3f7e70b0,0xbde1bc2e,0x3f7de0b1,0xbe039502,
0x3f800000,0x0,0x3f7fe129,0xbcfb49ba,0x3f7f84ab,0xbd7b2b74,0x3f7eea9d,0xbdbc3ac3,0x3ffe1324,0xbe7ab273,0x3f7cfe73,0xbe1c76de,0x3f7baccd,0xbe3b6ecf,0x3f7a1e84,0xbe5a3997,
0x3f800000,0x0,0x3f7fc38f,0xbd2fe007,0x3f7f0e58,0xbdafb680,0x3f7de0b1,0xbe039502,0x3ffc3b28,0xbeaf10a2,0x3f7a1e84,0xbe5a3997,0x3f778bc5,0xbe827dc0,0x3f748422,0xbe97a117,
0x3f800000,0x0,0x3f7f9c18,0xbd621469,0x3f7e70b0,0xbde1bc2e,0x3f7c7eb0,0xbe28defc,0x3ff9c79d,0xbee05c13,0x3f764d97,0xbe8b9507,0x3f721352,0xbea68f12,0x3f6d1c1d,0xbec1071e,
0x3f800000,0x0,0x3f7f6ac7,0xbd8a200a,0x3f7dabcc,0xbe09cf86,0x3f7ac516,0xbe4dee60,0x3ff6ba07,0xbf088e93,0x3f718f57,0xbea986c4,0x3f6b4b0c,0xbec9b953,0x3f63f473,0xbee900b7,
0x3f800000,0x0,0x3f7f2f9d,0xbda3308c,0x3f7cbfc9,0xbe22abb6,0x3f78b47b,0xbe72b651,0x3ff31447,0xbf209ae5,0x3f6be858,0xbec6d529,0x3f633c5a,0xbeebcbbb,0x3f591e6a,0xbf07a136,
0x3f800000,0x0,0x3f7eea9d,0xbdbc3ac3,0x3f7baccd,0xbe3b6ecf,0x3f764d97,0xbe8b9507,0x3feed89e,0xbf38442a,0x3f655e0b,0xbee363fa,0x3f59f26a,0xbf064b82,0x3f4cae79,0xbf19c200,
0x3f800000,0x0,0x3f7e9bc9,0xbdd53db9,0x3f7a7302,0xbe541501,0x3f73913f,0xbe9d9e78,0x3fea09a7,0xbf4f7bca,0x3f5df6be,0xbeff17b2,0x3f4f7a1f,0xbf15f6d9,0x3f3ebc1b,0xbf2ac082,
0x3f800000,0x0,0x3f7e4323,0xbdee3876,0x3f791298,0xbe6c9a7f,0x3f708066,0xbeaf713a,0x3fe4aa59,0xbf663375,0x3f55b993,0xbf0cead0,0x3f43e200,0xbf24d225,0x3f2f61a5,0xbf3a7ca4,
0x3f800000,0x0,0x3f7de0b1,0xbe039502,0x3f778bc5,0xbe827dc0,0x3f6d1c1d,0xbec1071e,0x3fdebe05,0xbf7c5d27,0x3f4cae79,0xbf19c200,0x3f373a23,0xbf32c8c9,0x3f1ebc12,0xbf48d8b3,
0x3f800000,0x0,0x3f7d7474,0xbe1008b7,0x3f75dec6,0xbe8e9a22,0x3f696591,0xbed25a09,0x3fd84853,0xbf88f59b,0x3f42de29,0xbf26050a,0x3f299415,0xbf3fc767,0x3f0cead0,0xbf55b993,
0x3f800000,0x0,0x3f7cfe73,0xbe1c76de,0x3f740bdd,0xbe9aa086,0x3f655e0b,0xbee363fa,0x3fd14d3d,0xbf93682a,0x3f385216,0xbf31a81d,0x3f1b02c6,0xbf4bbbf8,0x3ef41f07,0xbf6106f2,
0x3f800000,0x0,0x3f7c7eb0,0xbe28defc,0x3f721352,0xbea68f12,0x3f6106f2,0xbef41f07,0x3fc9d112,0xbf9d7fd1,0x3f2d1469,0xbf3ca003,0x3f0b9a6b,0xbf5695e5,0x3ecc9b8b,0xbf6aab7b,
0x3f800000,0x0,0x3f7bf531,0xbe354098,0x3f6ff573,0xbeb263ef,0x3f5c61c7,0xbf0242b1,0x3fc1d870,0xbfa73656,0x3f212ff9,0xbf46e22a,0x3ef6e0cb,0xbf604621,0x3ea395c5,0xbf7294f8,
0x3f800000,0x0,0x3f7b61fc,0xbe419b37,0x3f6db293,0xbebe1d4a,0x3f577026,0xbf0a48ad,0x3fb96842,0xbfb085bb,0x3f14b039,0xbf5064af,0x3ed53641,0xbf68bf3c,0x3e72b651,0xbf78b47b,
0x3f800000,0x0,0x3f7ac516,0xbe4dee60,0x3f6b4b0c,0xbec9b953,0x3f5233c6,0xbf121eb0,0x3fb085bb,0xbfb96842,0x3f07a136,0xbf591e6a,0x3eb263ef,0xbf6ff573,0x3e1c76de,0xbf7cfe73,
0x3f800000,0x0,0x3f7a1e84,0xbe5a3997,0x3f68bf3c,0xbed53641,0x3f4cae79,0xbf19c200,0x3fa73656,0xbfc1d870,0x3ef41f07,0xbf6106f2,0x3e8e9a22,0xbf75dec6,0x3d8a200a,0xbf7f6ac7,
0x3f800000,0x0,0x3f796e4e,0xbe667c66,0x3f660f88,0xbee0924f,0x3f46e22a,0xbf212ff9,0x3f9d7fd1,0xbfc9d112,0x3ed8106b,0xbf6816a8,0x3e541501,0xbf7a7302,0xbc96c9b6,0xbf7ff4e6,
0x3f800000,0x0,0x3f78b47b,0xbe72b651,0x3f633c5a,0xbeebcbbb,0x3f40d0da,0xbf286605,0x3f93682a,0xbfd14d3d,0x3ebb31a0,0xbf6e46be,0x3e09cf86,0xbf7dabcc,0xbdd53db9,0xbf7e9bc9,
0x3f800000,0x0,0x3f77f110,0xbe7ee6e1,0x3f604621,0xbef6e0cb,0x3f3a7ca4,0xbf2f61a5,0x3f88f59b,0xbfd84853,0x3e9d9e78,0xbf73913f,0x3d7b2b74,0xbf7f84ab,0xbe419b37,0xbf7b61fc,
0x3f800000,0x0,0x3f772417,0xbe8586ce,0x3f5d2d53,0xbf00e7e4,0x3f33e7bc,0xbf36206c,0x3f7c5d27,0xbfdebe05,0x3e7ee6e1,0xbf77f110,0xbc490e90,0xbf7ffb11,0xbe8b9507,0xbf764d97,
0x3f800000,0x0,0x3f764d97,0xbe8b9507,0x3f59f26a,0xbf064b82,0x3f2d1469,0xbf3ca003,0x3f663375,0xbfe4aa59,0x3e419b37,0xbf7b61fc,0xbdafb680,0xbf7f0e58,0xbeb554ec,0xbf6f6830,
0x3f800000,0x0,0x3f756d97,0xbe919ddd,0x3f5695e5,0xbf0b9a6b,0x3f26050a,0xbf42de29,0x3f4f7bca,0xbfea09a7,0x3e039502,0xbf7de0b1,0xbe22abb6,0xbf7cbfc9,0xbeddbe79,0xbf66becc,
0x3f800000,0x0,0x3f748422,0xbe97a117,0x3f531849,0xbf10d3cd,0x3f1ebc12,0xbf48d8b3,0x3f38442a,0xbfeed89e,0x3d8a200a,0xbf7f6ac7,0xbe6c9a7f,0xbf791298,0xbf0242b1,0xbf5c61c7,
0x3f800000,0x0,0x3f73913f,0xbe9d9e78,0x3f4f7a1f,0xbf15f6d9,0x3f173c07,0xbf4e8d90,0x3f209ae5,0xbff31447,0x3bc90f88,0xbf7ffec4,0xbe9aa086,0xbf740bdd,0xbf14b039,0xbf5064af,
0x3f800000,0x0,0x3f7294f8,0xbea395c5,0x3f4bbbf8,0xbf1b02c6,0x3f0f8784,0xbf53fac3,0x3f088e93,0xbff6ba07,0xbd621469,0xbf7f9c18,0xbebe1d4a,0xbf6db293,0xbf26050a,0xbf42de29,
0x3f800000,0x0,0x3f718f57,0xbea986c4,0x3f47de65,0xbf1ff6cb,0x3f07a136,0xbf591e6a,0x3ee05c13,0xbff9c79d,0xbdee3876,0xbf7e4323,0xbee0924f,0xbf660f88,0xbf36206c,0xbf33e7bc,
0x3f800000,0x0,0x3f708066,0xbeaf713a,0x3f43e200,0xbf24d225,0x3eff17b2,0xbf5df6be,0x3eaf10a2,0xbffc3b28,0xbe354098,0xbf7bf531,0xbf00e7e4,0xbf5d2d53,0xbf44e3f5,0xbf239da9,
0x3f800000,0x0,0x3f6f6830,0xbeb554ec,0x3f3fc767,0xbf299415,0x3eee9479,0xbf628210,0x3e7ab273,0xbffe1324,0xbe72b651,0xbf78b47b,0xbf10d3cd,0xbf531849,0xbf5233c6,0xbf121eb0,
0x3f800000,0x0,0x3f6e46be,0xbebb31a0,0x3f3b8f3b,0xbf2e3bde,0x3eddbe79,0xbf66becc,0x3e16a905,0xbfff4e6d,0xbe97a117,0xbf748422,0xbf1ff6cb,0xbf47de65,0xbf5df6be,0xbeff17b2,
0x3f800000,0x0,0x3f6d1c1d,0xbec1071e,0x3f373a23,0xbf32c8c9,0x3ecc9b8b,0xbf6aab7b,0x3d490ab0,0xbfffec43,0xbeb554ec,0xbf6f6830,0xbf2e3bde,0xbf3b8f3b,0xbf6816a8,0xbed8106b,
0x3f800000,0x0,0x3f7ffd39,0xbc16cb58,0x3f7ff4e6,0xbc96c9b6,0x3f7fe705,0xbce22a7a,0x3fffd397,0xbd96c32c,0x3f7fba9e,0xbd3c6dd5,0x3f7f9c18,0xbd621469,0x3f7f7808,0xbd83db0a,
0x3f800000,0x0,0x3f7ff0e3,0xbcafea69,0x3f7fc38f,0xbd2fe007,0x3f7f7808,0xbd83db0a,0x3fff0e58,0xbe2fb680,0x3f7e868b,0xbddb7d37,0x3f7de0b1,0xbe039502,0x3f7d1cdd,0xbe195be0,
0x3f800000,0x0,0x3f7fdaaf,0xbd0a342f,0x3f7f6ac7,0xbd8a200a,0x3f7eb069,0xbdcefdb7,0x3ffdabcc,0xbe89cf86,0x3f7c5d3a,0xbe2bf804,0x3f7ac516,0xbe4dee60,0x3f78e3d6,0xbe6fa8b2,
0x3f800000,0x0,0x3f7fba9e,0xbd3c6dd5,0x3f7eea9d,0xbdbc3ac3,0x3f7d906e,0xbe0cec4a,0x3ffbaccd,0xbebb6ecf,0x3f7940c0,0xbe698bba,0x3f764d97,0xbe8b9507,0x3f72d4eb,0xbea21887,
0x3f800000,0x0,0x3f7f90b1,0xbd6ea038,0x3f7e4323,0xbdee3876,0x3f7c187a,0xbe3228d4,0x3ff91298,0xbeec9a7f,0x3f75341d,0xbe931f35,0x3f708066,0xbeaf713a,0x3f6afb8c,0xbecb2aae,
0x3f800000,0x0,0x3f7f5ce9,0xbd9064b4,0x3f7d7474,0xbe1008b7,0x3f7a4910,0xbe57278f,0x3ff5dec6,0xbf0e9a22,0x3f703b37,0xbeb0eacb,0x3f696591,0xbed25a09,0x3f61668a,0xbef2bd43,
0x3f800000,0x0,0x3f7f1f49,0xbda973ba,0x3f7c7eb0,0xbe28defc,0x3f7822d1,0xbe7bdba4,0x3ff21352,0xbf268f12,0x3f6a5ad9,0xbece0bea,0x3f6106f2,0xbef41f07,0x3f5627fe,0xbf0c42c9,
0x3f800000,0x0,0x3f7ed7d4,0xbdc27c39,0x3f7b61fc,0xbe419b37,0x3f75a67b,0xbe901c2c,0x3fedb293,0xbf3e1d4a,0x3f6398ac,0xbeea6681,0x3f577026,0xbf0a48ad,0x3f495521,0xbf1e1e22,
0x3f800000,0x0,0x3f7e868b,0xbddb7d37,0x3f7a1e84,0xbe5a3997,0x3f72d4eb,0xbea21887,0x3fe8bf3c,0xbf553641,0x3f5bfb34,0xbf02ef9f,0x3f4cae79,0xbf19c200,0x3f3b0629,0xbf2ecef7,
0x3f800000,0x0,0x3f7e2b72,0xbdf475c0,0x3f78b47b,0xbe72b651,0x3f6faf1b,0xbeb3dca5,0x3fe33c5a,0xbf6bcbbb,0x3f5389c7,0xbf102dd5,0x3f40d0da,0xbf286605,0x3f2b561b,0xbf3e35c5,
0x3f800000,0x0,0x3f7dc68c,0xbe06b26e,0x3f772417,0xbe8586ce,0x3f6c3624,0xbec5625c,0x3fdd2d53,0xbf80e7e4,0x3f4a4c87,0xbf1ce11f,0x3f33e7bc,0xbf36206c,0x3f1a6293,0xbf4c3578,
0x3f800000,0x0,0x3f7d57de,0xbe1324ca,0x3f756d97,0xbe919ddd,0x3f686b39,0xbed6a399,0x3fd695e5,0xbf8b9a6b,0x3f404c5c,0xbf28fd41,0x3f26050a,0xbf42de29,0x3f084b92,0xbf58b3a1,
0x3f800000,0x0,0x3f7cdf6c,0xbe1f917b,0x3f73913f,0xbe9d9e78,0x3f644fac,0xbee79a5d,0x3fcf7a1f,0xbf95f6d9,0x3f3592e7,0xbf34768f,0x3f173c07,0xbf4e8d90,0x3eea6681,0xbf6398ac,
0x3f800000,0x0,0x3f7c5d3a,0xbe2bf804,0x3f718f57,0xbea986c4,0x3f5fe4e9,0xbef840c8,0x3fc7de65,0xbf9ff6cb,0x3f2a2a80,0xbf3f41fc,0x3f07a136,0xbf591e6a,0x3ec27b55,0xbf6cd007,
0x3f800000,0x0,0x3f7bd14d,0xbe3857ec,0x3f6f6830,0xbeb554ec,0x3f5b2c79,0xbf044889,0x3fbfc767,0xbfa99415,0x3f1e1e22,0xbf495521,0x3eee9479,0xbf628210,0x3e9920fe,0xbf74484b,
0x3f800000,0x0,0x3f7b3bab,0xbe44b0b9,0x3f6d1c1d,0xbec1071e,0x3f5627fe,0xbf0c42c9,0x3fb73a23,0xbfb2c8c9,0x3f11796b,0xbf52a649,0x3ecc9b8b,0xbf6aab7b,0x3e5d4b1a,0xbf79f35e,
0x3f800000,0x0,0x3f7a9c59,0xbe5101f1,0x3f6aab7b,0xbecc9b8b,0x3f50d937,0xbf140c5f,0x3fae3bde,0xbfbb8f3b,0x3f044889,0xbf5b2c79,0x3ea986c4,0xbf718f57,0x3e06b26e,0xbf7dc68c,
0x3f800000,0x0,0x3f79f35e,0xbe5d4b1a,0x3f6816a8,0xbed8106b,0x3f4b41fa,0xbf1ba299,0x3fa4d225,0xbfc3e200,0x3eed3063,0xbf62df7b,0x3e8586ce,0xbf772417,0x3d3c6dd5,0xbf7fba9e,
0x3f800000,0x0,0x3f7940c0,0xbe698bba,0x3f655e0b,0xbee363fa,0x3f456439,0xbf2302d3,0x3f9b02c6,0xbfcbbbf8,0x3ed0eb2a,0xbf69b7e4,0x3e419b37,0xbf7b61fc,0xbd2351cb,0xbf7fcbe2,
0x3f800000,0x0,0x3f788486,0xbe75c35a,0x3f628210,0xbeee9479,0x3f3f41fc,0xbf2a2a80,0x3f90d3cd,0xbfd31849,0x3eb3dca5,0xbf6faf1b,0x3dee3876,0xbf7e4323,0xbe007745,0xbf7dfa38,
0x3f800000,0x0,0x3f77beb7,0xbe80f8c0,0x3f5f8327,0xbef9a02d,0x3f38dd65,0xbf311722,0x3f864b82,0xbfd9f26a,0x3e9620d2,0xbf74bf62,0x3d2fe007,0xbf7fc38f,0xbe57278f,0xbf7a4910,
0x3f800000,0x0,0x3f76ef5b,0xbe870ada,0x3f5c61c7,0xbf0242b1,0x3f3238aa,0xbf37c655,0x3f76e0cb,0xbfe04621,0x3e6fa8b2,0xbf78e3d6,0xbcfb49ba,0xbf7fe129,0xbe9620d2,0xbf74bf62,
0x3f800000,0x0,0x3f76167a,0xbe8d17c0,0x3f591e6a,0xbf07a136,0x3f2b561b,0xbf3e35c5,0x3f60924f,0xbfe60f88,0x3e3228d4,0xbf7c187a,0xbdd53db9,0xbf7e9bc9,0xbebf926f,0xbf6d67a1,
0x3f800000,0x0,0x3f75341d,0xbe931f35,0x3f55b993,0xbf0cead0,0x3f24381a,0xbf446337,0x3f49b953,0xbfeb4b0c,0x3de7fa9a,0xbf7e5a38,0xbe354098,0xbf7bf531,0xbee79a5d,0xbf644fac,
0x3f800000,0x0,0x3f74484b,0xbe9920fe,0x3f5233c6,0xbf121eb0,0x3f1ce11f,0xbf4a4c87,0x3f3263ef,0xbfeff573,0x3d55880e,0xbf7fa6e3,0xbe7ee6e1,0xbf77f110,0xbf06f686,0xbf5988ad,
0x3f800000,0x0,0x3f73530e,0xbe9f1cdf,0x3f4e8d90,0xbf173c07,0x3f1553b7,0xbf4fefa8,0x3f1aa086,0xbff40bdd,0xbc16cb58,0xbf7ffd39,0xbea395c5,0xbf7294f8,0xbf19210f,0xbf4d26fd,
0x3f800000,0x0,0x3f725470,0xbea5129f,0x3f4ac77f,0xbf1c420c,0x3f0d9281,0xbf554aa4,0x3f027dc0,0xbff78bc5,0xbd9064b4,0xbf7f5ce9,0xbec6d529,0xbf6be858,0xbf2a2a80,0xbf3f41fc,
0x3f800000,0x0,0x3f714c7a,0xbeab0201,0x3f46e22a,0xbf212ff9,0x3f05a02c,0xbf5a5ba0,0x3ed41501,0xbffa7302,0xbe06b26e,0xbf7dc68c,0xbee900b7,0xbf63f473,0xbf39f2ac,0xbf2ff3e6,
0x3f800000,0x0,0x3f703b37,0xbeb0eacb,0x3f42de29,0xbf26050a,0x3efafef7,0xbf5f20db,0x3ea2abb6,0xbffcbfc9,0xbe44b0b9,0xbf7b3bab,0xbf04f484,0xbf5ac450,0xbf485bca,0xbf1f599f,
0x3f800000,0x0,0x3f6f20b0,0xbeb6ccc3,0x3f3ebc1b,0xbf2ac082,0x3eea6681,0xbf6398ac,0x3e61bc2e,0xbffe70b0,0xbe80f8c0,0xbf77beb7,0xbf14b039,0xbf5064af,0xbf554aa4,0xbf0d9281,
0x3f800000,0x0,0x3f6dfcf2,0xbebca7af,0x3f3a7ca4,0xbf2f61a5,0x3ed97cb9,0xbf67c187,0x3dfb2b74,0xbfff84ab,0xbe9f1cdf,0xbf73530e,0xbf239da9,0xbf44e3f5,0xbf60a6cf,0xbef58035,
0x3f800000,0x0,0x3f6cd007,0xbec27b55,0x3f36206c,0xbf33e7bc,0x3ec8477c,0xbf6b99fb,0x3cc90e90,0xbffffb11,0xbebca7af,0xbf6dfcf2,0xbf31a81d,0xbf385216,0xbf6a5ad9,0xbece0bea,
0x3f800000,0x0,0x0,0x0,0x0,0x0,0x0,0x0,0x0,0x0,0x0,0x0,0x0,0x0,0x0,0x0,
0x0,0x0,0x0,0x0,0x0,0x0,0x0,0x0,0x0,0x0,0x0,0x0,0x0,0x0,0x0,0x0,
0x0,0x0,0x3e000000,0xbf20dff7,0x3ed0c429,0x0,0x3e000000,0x3e61f78b,0x3e0a8bd4,0x0,0x3e000000,0x3d5413cd,0x3d5df9ad,0x0,0x3e000000,0x3cf043ab,
0x0,0x0,0x3e000000,0x3ccbafaf,0xbd5df9ad,0x0,0x3e000000,0x3cf043ab,0xbe0a8bd4,0x0,0x3e000000,0x3d5413cd,0xbed0c429,0x0,0x3e000000,0x3e61f78b,
0x0,0x0,0x0,0x0,0x3f000000,0x0,0x0,0x3f000000,0x0,0x0,0x0,0x0,0x0,0x0,0x0,0x0,
0x0,0x0,0x0,0x0,0x0,0x0,0x0,0x0,0x0,0x0,0x0,0x0,0x3f000000,0x0,0x0,0xbf000000,
0x0,0x0,0x3e000000,0xbe3f90c7,0xbe8b7e3f,0x0,0x3e000000,0xbeb641af,0x3ea73d75,0x0,0x3e000000,0x3e9a827a,0x3da61ad1,0x0,0x3e000000,0x3dd906bd,
0x0,0x0,0x3e000000,0x3dab0dc1,0xbda61ad1,0x0,0x3e000000,0x3dd906bd,0xbea73d75,0x0,0x3e000000,0x3e9a827a,0x3e8b7e3f,0x0,0x3e000000,0xbeb641af,
0x0,0x0,0x0,0x0,0x0,0x0,0x0,0x0,0x3f000000,0x0,0x0,0x3f000000,0x0,0x0,0x0,0x0,
0x0,0x0,0x0,0x0,0x0,0x0,0x0,0x0,0x3f000000,0x0,0x0,0xbf000000,0x0,0x0,0x0,0x0,
0x0,0x0,0x3e000000,0xbdab0dc1,0xbda61ad1,0x0,0x3e000000,0xbdd906bd,0xbea73d75,0x0,0x3e000000,0xbe9a827a,0x3e8b7e3f,0x0,0x3e000000,0x3eb641af,
0x0,0x0,0x3e000000,0x3e3f90c7,0xbe8b7e3f,0x0,0x3e000000,0x3eb641af,0x3ea73d75,0x0,0x3e000000,0xbe9a827a,0x3da61ad1,0x0,0x3e000000,0xbdd906bd,
0x0,0x0,0x0,0x0,0x0,0x0,0x0,0x0,0x0,0x0,0x0,0x0,0x3f000000,0x0,0x0,0x3f000000,
0x0,0x0,0x0,0x0,0x3f000000,0x0,0x0,0xbf000000,0x0,0x0,0x0,0x0,0x0,0x0,0x0,0x0,
0x0,0x0,0x3e000000,0xbccbafaf,0xbd5df9ad,0x0,0x3e000000,0xbcf043ab,0xbe0a8bd4,0x0,0x3e000000,0xbd5413cd,0xbed0c429,0x0,0x3e000000,0xbe61f78b,
0x0,0x0,0x3e000000,0x3f20dff7,0x3ed0c429,0x0,0x3e000000,0xbe61f78b,0x3e0a8bd4,0x0,0x3e000000,0xbd5413cd,0x3d5df9ad,0x0,0x3e000000,0xbcf043ab,
};

struct Params {
    const __nv_bfloat16 *wr, *wi, *lre, *lim, *ldt, *dsk;
    float* out;
};

struct cf { float x, y; };
#define YIELD() asm volatile("pmevent 1;")
#define YS 14
#define YIELD_S1() do { if (YS & 1) YIELD(); } while (0)
#define YIELD_S2() do { if (YS & 2) YIELD(); } while (0)
#define YIELD_S3() do { if (YS & 4) YIELD(); } while (0)
__device__ __forceinline__ uint32_t smem_u32(const void* p) { return (uint32_t)__cvta_generic_to_shared(p); }
__device__ __forceinline__ void mbar_init(uint32_t a, uint32_t c) { asm volatile("mbarrier.init.shared::cta.b64 [%0], %1;" ::"r"(a), "r"(c) : "memory"); }
__device__ __forceinline__ void mbar_expect_tx(uint32_t a, uint32_t b) { asm volatile("mbarrier.arrive.expect_tx.shared::cta.b64 _, [%0], %1;" ::"r"(a), "r"(b) : "memory"); }
__device__ __forceinline__ void mbar_arrive(uint32_t a) { asm volatile("mbarrier.arrive.shared::cta.b64 _, [%0];" ::"r"(a) : "memory"); }
__device__ __forceinline__ void warp_arrive(uint32_t a) {
    __syncwarp();
    asm volatile("{.reg .pred p; elect.sync _|p, 0xffffffff; @p mbarrier.arrive.shared::cta.b64 _, [%0];}" ::"r"(a) : "memory");
}
__device__ __forceinline__ uint32_t mbar_try(uint32_t a, uint32_t ph) {
    uint32_t ok;
    asm volatile("{.reg .pred p; mbarrier.try_wait.parity.shared::cta.b64 p, [%1], %2; selp.u32 %0, 1, 0, p;}" : "=r"(ok) : "r"(a), "r"(ph) : "memory");
    return ok;
}
__device__ __forceinline__ void mbar_wait(uint32_t a, uint32_t ph) {
    uint32_t ok, n = 0;
    do { ok = mbar_try(a, ph); } while (!ok && ++n < SPIN_LIMIT);
}
__device__ __forceinline__ void mbar_wait_fast(uint32_t a, uint32_t ph) { if (!mbar_try(a, ph)) mbar_wait(a, ph); }
__device__ __forceinline__ unsigned ld_rlx(const unsigned* p) { unsigned v; asm volatile("ld.relaxed.gpu.global.u32 %0, [%1];" : "=r"(v) : "l"(p) : "memory"); return v; }
__device__ __forceinline__ void wait_cnt(const unsigned* p, unsigned target) {
    unsigned n = 0;
    while ((int)(ld_rlx(p) - target) < 0 && ++n < SPIN_LIMIT) __nanosleep(20);
}
__device__ __forceinline__ void red_hint(unsigned* p) { asm volatile("red.relaxed.gpu.global.add.u32 [%0], 1;" ::"l"(p) : "memory"); }
__device__ __forceinline__ void fence_async_sm() { asm volatile("fence.proxy.async.shared::cta;" ::: "memory"); }
#define bar_sync(id, n) asm volatile("bar.sync %0, %1;" ::"n"(id), "n"(n) : "memory")
#define bar_arrive(id, n) asm volatile("bar.arrive %0, %1;" ::"n"(id), "n"(n) : "memory")
__device__ __forceinline__ bool elect_one() {
    uint32_t r;
    asm volatile("{.reg .pred p; elect.sync _|p, 0xffffffff; selp.u32 %0, 1, 0, p;}" : "=r"(r));
    return r != 0;
}

__device__ __forceinline__ void tma2d(uint32_t dst, const CUtensorMap* m, int c0, int c1, uint32_t bar) {
    asm volatile("cp.async.bulk.tensor.2d.shared::cluster.global.mbarrier::complete_tx::bytes [%0], [%1, {%3,%4}], [%2];" ::"r"(dst), "l"(m), "r"(bar), "r"(c0), "r"(c1) : "memory");
}
__device__ __forceinline__ void tma3d(uint32_t dst, const CUtensorMap* m, int c0, int c1, int c2, uint32_t bar) {
    asm volatile("cp.async.bulk.tensor.3d.shared::cluster.global.mbarrier::complete_tx::bytes [%0], [%1, {%3,%4,%5}], [%2];" ::"r"(dst), "l"(m), "r"(bar), "r"(c0), "r"(c1), "r"(c2) : "memory");
}
__device__ __forceinline__ void tma4d_mc(uint32_t dst, const CUtensorMap* m, int c0, int c1, int c2, int c3, uint32_t bar) {
    asm volatile("cp.async.bulk.tensor.4d.shared::cluster.global.mbarrier::complete_tx::bytes.multicast::cluster [%0], [%1, {%3,%4,%5,%6}], [%2], %7;" ::"r"(dst), "l"(m), "r"(bar), "r"(c0), "r"(c1), "r"(c2), "r"(c3), "h"((uint16_t)3) : "memory");
}
__device__ __forceinline__ void tma4d(uint32_t dst, const CUtensorMap* m, int c0, int c1, int c2, int c3, uint32_t bar) {
    asm volatile("cp.async.bulk.tensor.4d.shared::cluster.global.mbarrier::complete_tx::bytes [%0], [%1, {%3,%4,%5,%6}], [%2];" ::"r"(dst), "l"(m), "r"(bar), "r"(c0), "r"(c1), "r"(c2), "r"(c3) : "memory");
}
__device__ __forceinline__ void tma2d_st(const CUtensorMap* m, int c0, int c1, uint32_t src) {
    asm volatile("cp.async.bulk.tensor.2d.global.shared::cta.bulk_group [%0, {%2,%3}], [%1];" ::"l"(m), "r"(src), "r"(c0), "r"(c1) : "memory");
}
__device__ __forceinline__ void tma5d(uint32_t dst, const CUtensorMap* m, int c0, int c1, int c2, int c3, int c4, uint32_t bar) {
    asm volatile("cp.async.bulk.tensor.5d.shared::cluster.global.mbarrier::complete_tx::bytes [%0], [%1, {%3,%4,%5,%6,%7}], [%2];" ::"r"(dst), "l"(m), "r"(bar), "r"(c0), "r"(c1), "r"(c2), "r"(c3), "r"(c4) : "memory");
}
__device__ __forceinline__ void bulk_ld(uint32_t dst, const void* src, uint32_t n, uint32_t bar) {
    asm volatile("cp.async.bulk.shared::cluster.global.mbarrier::complete_tx::bytes [%0], [%1], %2, [%3];" ::"r"(dst), "l"(src), "r"(n), "r"(bar) : "memory");
}
__device__ __forceinline__ void bulk_st(void* dst, uint32_t src, uint32_t n) {
    asm volatile("cp.async.bulk.global.shared::cta.bulk_group [%0], [%1], %2;" ::"l"(dst), "r"(src), "r"(n) : "memory");
}
__device__ __forceinline__ void bulk_commit() { asm volatile("cp.async.bulk.commit_group;" ::: "memory"); }
__device__ __forceinline__ void bulk_wait_read() { asm volatile("cp.async.bulk.wait_group.read 0;" ::: "memory"); }
__device__ __forceinline__ void bulk_wait_all() { asm volatile("cp.async.bulk.wait_group 0;" ::: "memory"); }
__device__ __forceinline__ void stsm4(uint32_t a, uint32_t r0, uint32_t r1, uint32_t r2, uint32_t r3) {
    asm volatile("stmatrix.sync.aligned.m8n8.x4.shared.b16 [%0], {%1,%2,%3,%4};" ::"r"(a), "r"(r0), "r"(r1), "r"(r2), "r"(r3) : "memory");
}
__device__ __forceinline__ void sts128(uint32_t a, uint32_t r0, uint32_t r1, uint32_t r2, uint32_t r3) {
    asm volatile("st.shared.v4.b32 [%0], {%1,%2,%3,%4};" ::"r"(a), "r"(r0), "r"(r1), "r"(r2), "r"(r3) : "memory");
}
__device__ __forceinline__ void lds128f(uint32_t a, float& x, float& y, float& z, float& u) { asm volatile("ld.shared.v4.f32 {%0,%1,%2,%3}, [%4];" : "=f"(x), "=f"(y), "=f"(z), "=f"(u) : "r"(a) : "memory"); }
__device__ __forceinline__ cf lds_cf(uint32_t a) { cf v; asm volatile("ld.shared.v2.f32 {%0,%1}, [%2];" : "=f"(v.x), "=f"(v.y) : "r"(a) : "memory"); return v; }
__device__ __forceinline__ void stg128(const void* a, uint32_t r0, uint32_t r1, uint32_t r2, uint32_t r3) {
    asm volatile("st.global.v4.b32 [%0], {%1,%2,%3,%4};" ::"l"(a), "r"(r0), "r"(r1), "r"(r2), "r"(r3) : "memory");
}
__device__ __forceinline__ int fresh_lane() { int v; asm volatile("mov.u32 %0, %%laneid;" : "=r"(v)); return v; }
__device__ __forceinline__ uint32_t opaque32(uint32_t v) { asm volatile("" : "+r"(v)); return v; }
__device__ __forceinline__ const uint8_t* padd(const void* base, uint32_t off) {
    uint64_t r;
    asm("{.reg .u32 l, h; mov.b64 {l, h}, %1; add.cc.u32 l, l, %2; addc.u32 h, h, 0; mov.b64 %0, {l, h};}" : "=l"(r) : "l"(base), "r"(off));
    return (const uint8_t*)r;
}
template <int N, int STRIDE> __device__ __forceinline__ void ldtab(uint32_t (&v)[4 * N], uint32_t off) {
    const uint8_t* a = padd(g_tab, off);
#pragma unroll
    for (int i = 0; i < N; i++)
        asm volatile("ld.global.nc.v4.b32 {%0,%1,%2,%3}, [%4];" : "=r"(v[4 * i]), "=r"(v[4 * i + 1]), "=r"(v[4 * i + 2]), "=r"(v[4 * i + 3]) : "l"(a + i * STRIDE));
}
template <int STRIDE> __device__ __forceinline__ void ldtab_cf(cf (&t)[8], uint32_t off) {
    uint32_t v[16];
    ldtab<4, STRIDE>(v, off);
#pragma unroll
    for (int i = 0; i < 8; i++) t[i] = {__uint_as_float(v[2 * i]), __uint_as_float(v[2 * i + 1])};
}
__device__ __forceinline__ uint32_t lds16(uint32_t a) { uint32_t v; asm volatile("ld.shared.u16 %0, [%1];" : "=r"(v) : "r"(a)); return v; }
__device__ __forceinline__ unsigned get_epoch(uint32_t bars) {
    mbar_wait(bars + B_EP, 0);
    unsigned e;
    asm volatile("ld.shared.u32 %0, [%1];" : "=r"(e) : "r"(bars + B_EPOCH) : "memory");
    return e;
}
__device__ __forceinline__ void sts64(uint32_t a, uint32_t x, uint32_t y) { asm volatile("st.shared.v2.b32 [%0], {%1,%2};" ::"r"(a), "r"(x), "r"(y) : "memory"); }
__device__ __forceinline__ uint32_t pk(float lo, float hi) { uint32_t r; asm("cvt.rn.bf16x2.f32 %0, %1, %2;" : "=r"(r) : "f"(hi), "f"(lo)); return r; }
__device__ __forceinline__ float bf2f(unsigned short v) { return __uint_as_float((uint32_t)v << 16); }

__device__ __forceinline__ uint64_t mkdesc(uint32_t addr, uint32_t lbo, uint32_t sbo, uint32_t swz) {
    return (uint64_t)((addr & 0x3FFFF) >> 4) | ((uint64_t)(lbo >> 4) << 16) | ((uint64_t)(sbo >> 4) << 32) | ((uint64_t)swz << 62);
}
__device__ __forceinline__ uint64_t opaque(uint64_t v) { asm volatile("" : "+l"(v)); return v; }
__device__ __forceinline__ void wg_fence() { asm volatile("wgmma.fence.sync.aligned;" ::: "memory"); }
__device__ __forceinline__ void wg_commit() { asm volatile("wgmma.commit_group.sync.aligned;" ::: "memory"); }
template <int N> __device__ __forceinline__ void wg_wait() { asm volatile("wgmma.wait_group.sync.aligned %0;" ::"n"(N) : "memory"); }
template <int N> __device__ __forceinline__ void pin(float (&d)[N]) {
#pragma unroll
    for (int i = 0; i < N; i++) asm volatile("" : "+f"(d[i])::"memory");
}
template <int N> __device__ __forceinline__ void pinu(uint32_t (&d)[N]) {
#pragma unroll
    for (int i = 0; i < N; i++) asm volatile("" : "+r"(d[i])::"memory");
}

#define R8(d, o) "+f"(d[o]), "+f"(d[o + 1]), "+f"(d[o + 2]), "+f"(d[o + 3]), "+f"(d[o + 4]), "+f"(d[o + 5]), "+f"(d[o + 6]), "+f"(d[o + 7])
#define L8 "%0,%1,%2,%3,%4,%5,%6,%7"
#define L32 L8 ",%8,%9,%10,%11,%12,%13,%14,%15,%16,%17,%18,%19,%20,%21,%22,%23,%24,%25,%26,%27,%28,%29,%30,%31"
#define L56 L32 ",%32,%33,%34,%35,%36,%37,%38,%39,%40,%41,%42,%43,%44,%45,%46,%47,%48,%49,%50,%51,%52,%53,%54,%55"
#define L64 L56 ",%56,%57,%58,%59,%60,%61,%62,%63"

template <int O, int TA, int TB, int N> __device__ __forceinline__ void mma128_ss(float (&d)[N], uint64_t da, uint64_t db, int sc) {
    asm volatile("{.reg .pred p; setp.ne.b32 p, %66, 0;\n"
                 "wgmma.mma_async.sync.aligned.m64n128k16.f32.bf16.bf16 {" L64 "}, %64, %65, p, 1, 1, %67, %68;}"
                 : R8(d, O), R8(d, O + 8), R8(d, O + 16), R8(d, O + 24), R8(d, O + 32), R8(d, O + 40), R8(d, O + 48), R8(d, O + 56)
                 : "l"(da), "l"(db), "r"(sc), "n"(TA), "n"(TB));
}
template <int O, int TB> __device__ __forceinline__ void mma128_rs(float (&d)[128], uint32_t a0, uint32_t a1, uint32_t a2, uint32_t a3, uint64_t db, int sc) {
    asm volatile("{.reg .pred p; setp.ne.b32 p, %69, 0;\n"
                 "wgmma.mma_async.sync.aligned.m64n128k16.f32.bf16.bf16 {" L64 "}, {%64,%65,%66,%67}, %68, p, 1, 1, %70;}"
                 : R8(d, O), R8(d, O + 8), R8(d, O + 16), R8(d, O + 24), R8(d, O + 32), R8(d, O + 40), R8(d, O + 48), R8(d, O + 56)
                 : "r"(a0), "r"(a1), "r"(a2), "r"(a3), "l"(db), "r"(sc), "n"(TB));
}
template <int TB> __device__ __forceinline__ void mma64_rs(float (&d)[32], uint32_t a0, uint32_t a1, uint32_t a2, uint32_t a3, uint64_t db, int sc) {
    asm volatile("{.reg .pred p; setp.ne.b32 p, %37, 0;\n"
                 "wgmma.mma_async.sync.aligned.m64n64k16.f32.bf16.bf16 {" L32 "}, {%32,%33,%34,%35}, %36, p, 1, 1, %38;}"
                 : R8(d, 0), R8(d, 8), R8(d, 16), R8(d, 24)
                 : "r"(a0), "r"(a1), "r"(a2), "r"(a3), "l"(db), "r"(sc), "n"(TB));
}
__device__ __forceinline__ void mma112_ss(float (&d)[64], uint64_t da, uint64_t db, int sc) {
    asm volatile("{.reg .pred p; setp.ne.b32 p, %58, 0;\n"
                 "wgmma.mma_async.sync.aligned.m64n112k16.f32.bf16.bf16 {" L56 "}, %56, %57, p, 1, 1, 0, 1;}"
                 : R8(d, 8), R8(d, 16), R8(d, 24), R8(d, 32), R8(d, 40), R8(d, 48), R8(d, 56)
                 : "l"(da), "l"(db), "r"(sc));
}
__device__ __forceinline__ void mma16_rs(float (&d)[64], uint32_t a0, uint32_t a1, uint32_t a2, uint32_t a3, uint64_t db, int sc) {
    asm volatile("{.reg .pred p; setp.ne.b32 p, %13, 0;\n"
                 "wgmma.mma_async.sync.aligned.m64n16k16.f32.bf16.bf16 {" L8 "}, {%8,%9,%10,%11}, %12, p, 1, 1, 1;}"
                 : R8(d, 0)
                 : "r"(a0), "r"(a1), "r"(a2), "r"(a3), "l"(db), "r"(sc));
}

__device__ __forceinline__ cf cmul(cf a, cf b) { return {fmaf(a.x, b.x, -a.y * b.y), fmaf(a.x, b.y, a.y * b.x)}; }
__device__ __forceinline__ cf cmulc(cf a, cf b) { return {fmaf(a.x, b.x, a.y * b.y), fmaf(a.y, b.x, -a.x * b.y)}; }
__device__ __forceinline__ cf cfma(cf a, cf b, cf c) { return {fmaf(a.x, b.x, fmaf(-a.y, b.y, c.x)), fmaf(a.x, b.y, fmaf(a.y, b.x, c.y))}; }
__device__ __forceinline__ cf csq(cf a) { return {fmaf(a.x, a.x, -a.y * a.y), (a.x * a.y) * 2.f}; }
__device__ __forceinline__ cf csel(int c, cf a, cf b) {
    cf r;
    asm("{.reg .pred p; setp.ne.s32 p, %2, 0; selp.f32 %0, %3, %5, p; selp.f32 %1, %4, %6, p;}" : "=f"(r.x), "=f"(r.y) : "r"(c), "f"(a.x), "f"(a.y), "f"(b.x), "f"(b.y));
    return r;
}
__device__ __forceinline__ cf cadd(cf a, cf b) { return {a.x + b.x, a.y + b.y}; }
__device__ __forceinline__ cf csub(cf a, cf b) { return {a.x - b.x, a.y - b.y}; }
__device__ __forceinline__ cf twice_minus(cf a, cf s) { return {fmaf(2.f, a.x, -s.x), fmaf(2.f, a.y, -s.y)}; }
__device__ __forceinline__ cf twid(int m, int M) {
    int r = ((m + M / 2) & (M - 1)) - M / 2;
    float s, c;
    __sincosf((float)r * (-6.283185307179586f / (float)M), &s, &c);
    return {c, s};
}
struct c2 { cf a, b; };
#define YP1 3
#define YP3 3
template <int Y> __device__ __forceinline__ void fin(c2& u) { if (Y & 1) asm volatile("pmevent 1;" : "+f"(u.a.x), "+f"(u.a.y), "+f"(u.b.x), "+f"(u.b.y)); }
template <int Y> __device__ __forceinline__ void fin(c2& u, c2& v) {
    if (Y & 2) asm volatile("pmevent 1;" : "+f"(u.a.x), "+f"(u.a.y), "+f"(u.b.x), "+f"(u.b.y), "+f"(v.a.x), "+f"(v.a.y), "+f"(v.b.x), "+f"(v.b.y));
}
__device__ __forceinline__ c2 mul2(c2 u, cf t) { return {cmul(u.a, t), cmul(u.b, t)}; }
__device__ __forceinline__ c2 mul2(c2 u, c2 t) { return {cmul(u.a, t.a), cmul(u.b, t.b)}; }
__device__ __forceinline__ c2 fma2(c2 u, cf t, c2 c) { return {cfma(u.a, t, c.a), cfma(u.b, t, c.b)}; }
__device__ __forceinline__ c2 fma2(c2 u, c2 t, c2 c) { return {cfma(u.a, t.a, c.a), cfma(u.b, t.b, c.b)}; }
__device__ __forceinline__ c2 twm2(c2 u, c2 s) { return {twice_minus(u.a, s.a), twice_minus(u.b, s.b)}; }
template <int Y> __device__ __forceinline__ void bfly(c2& u, c2& v) { const c2 t = u; u = {cadd(t.a, v.a), cadd(t.b, v.b)}; v = {csub(t.a, v.a), csub(t.b, v.b)}; fin<Y>(u, v); }
template <int Y> __device__ __forceinline__ void bfly_mi(c2& u, c2& v) {
    const c2 t = u, z = v;
    u = {{t.a.x + z.a.y, t.a.y - z.a.x}, {t.b.x + z.b.y, t.b.y - z.b.x}};
    v = {{t.a.x - z.a.y, t.a.y + z.a.x}, {t.b.x - z.b.y, t.b.y + z.b.x}};
    fin<Y>(u, v);
}
template <int Y> __device__ __forceinline__ void bfly_s(c2& u, c2& v) {
    const float s = 0.70710678118654752f;
    const c2 t = u, z = v;
    u = {{fmaf(s, z.a.x, t.a.x), fmaf(s, z.a.y, t.a.y)}, {fmaf(s, z.b.x, t.b.x), fmaf(s, z.b.y, t.b.y)}};
    v = {{fmaf(-s, z.a.x, t.a.x), fmaf(-s, z.a.y, t.a.y)}, {fmaf(-s, z.b.x, t.b.x), fmaf(-s, z.b.y, t.b.y)}};
    fin<Y>(u, v);
}
template <int Y, class T> __device__ __forceinline__ void bfly_tw(c2& u0, c2& v0, T t0, c2& u1, c2& v1, T t1) {
    v0 = fma2(v0, t0, u0); fin<Y>(v0);
    v1 = fma2(v1, t1, u1); fin<Y>(v1);
    const c2 a = twm2(u0, v0), b = twm2(u1, v1);
    u0 = v0; u1 = v1; v0 = a; v1 = b;
    fin<Y>(v0, v1);
}
template <bool TW, int Y> __device__ __forceinline__ void dft8(c2 (&v)[8], const cf (&tw)[8]) {
    if (TW) {
#pragma unroll
        for (int n = 1; n < 4; n++) { v[n] = mul2(v[n], tw[n]); fin<Y>(v[n]); }
        bfly_tw<Y>(v[0], v[4], tw[4], v[2], v[6], tw[6]);
        bfly_tw<Y>(v[1], v[5], tw[5], v[3], v[7], tw[7]);
    } else {
#pragma unroll
        for (int n = 0; n < 4; n++) bfly<Y>(v[n], v[n + 4]);
    }
    bfly<Y>(v[0], v[2]); bfly_mi<Y>(v[4], v[6]);
    bfly<Y>(v[1], v[3]); bfly_mi<Y>(v[5], v[7]);
    v[5] = {{v[5].a.x + v[5].a.y, v[5].a.y - v[5].a.x}, {v[5].b.x + v[5].b.y, v[5].b.y - v[5].b.x}};
    v[7] = {{v[7].a.y - v[7].a.x, -v[7].a.x - v[7].a.y}, {v[7].b.y - v[7].b.x, -v[7].b.x - v[7].b.y}};
    fin<Y>(v[5], v[7]);
    bfly<Y>(v[0], v[1]); bfly_s<Y>(v[4], v[5]); bfly_mi<Y>(v[2], v[3]); bfly_s<Y>(v[6], v[7]);
    const c2 t1 = v[1], t3 = v[3];
    v[1] = v[4]; v[4] = t1; v[3] = v[6]; v[6] = t3;
}

__device__ __forceinline__ void gather(uint64_t (&fv)[4], const uint8_t* a, int n) {
    asm volatile("{.reg .pred p0, p1, p2, p3;\n"
                 "setp.ge.s32 p0, %5, 0; setp.ge.s32 p1, %5, 4; setp.ge.s32 p2, %5, 8; setp.ge.s32 p3, %5, 12;\n"
                 "@p0 ld.relaxed.gpu.global.b64 %0, [%4]; @p1 ld.relaxed.gpu.global.b64 %1, [%4+-32768];\n"
                 "@p2 ld.relaxed.gpu.global.b64 %2, [%4+-65536]; @p3 ld.relaxed.gpu.global.b64 %3, [%4+-98304];}"
                 : "+l"(fv[0]), "+l"(fv[1]), "+l"(fv[2]), "+l"(fv[3]) : "l"(a), "r"(n) : "memory");
}
__device__ __forceinline__ cf as_cf(uint64_t v) { cf r; asm("mov.b64 {%0,%1}, %2;" : "=f"(r.x), "=f"(r.y) : "l"(v)); return r; }
template <int H> __device__ __forceinline__ void prescale(float (&u)[64], const float (&d)[128], cf gam) {
#pragma unroll
    for (int i = 0; i < 32; i += 2) {
        const int r = 2 * i + 2 * H;
        c2 v = mul2(c2{{d[r], -d[64 + r]}, {d[r + 1], -d[65 + r]}}, gam);
        if (YS & 2) asm volatile("pmevent 1;" : "+f"(v.a.x), "+f"(v.a.y), "+f"(v.b.x), "+f"(v.b.y));
        u[i] = v.a.x; u[32 + i] = v.a.y; u[i + 1] = v.b.x; u[33 + i] = v.b.y;
    }
}
__device__ __forceinline__ void scan2(const float (&u)[64], cf lam, cf st, const uint8_t* hptr, uint32_t hm, uint32_t hb, uint32_t& keep) {
    uint32_t hp[32];
#pragma unroll
    for (int jj = 0; jj < 4; jj++) {
        cf v[8];
#pragma unroll
        for (int i = 0; i < 8; i++) v[i] = st = cfma(lam, st, {u[8 * jj + i], u[32 + 8 * jj + i]});
        const int o = 8 * jj;
        hp[o] = pk(v[0].x, v[2].x); hp[o + 1] = pk(v[4].x, v[6].x); hp[o + 2] = pk(v[1].x, v[3].x); hp[o + 3] = pk(v[5].x, v[7].x);
        hp[o + 4] = pk(v[0].y, v[2].y); hp[o + 5] = pk(v[4].y, v[6].y); hp[o + 6] = pk(v[1].y, v[3].y); hp[o + 7] = pk(v[5].y, v[7].y);
        hp[o + jj] = (hp[o + jj] & hm) | hb;
        hp[o + 4 + jj] = (hp[o + 4 + jj] & hm) | hb;
        stg128(hptr + (jj >> 1) * 8192 + (jj & 1) * 512, hp[o], hp[o + 1], hp[o + 2], hp[o + 3]);
        stg128(hptr + 16384 + (jj >> 1) * 8192 + (jj & 1) * 512, hp[o + 4], hp[o + 5], hp[o + 6], hp[o + 7]);
        YIELD_S3();
        if (jj > 0) {
#pragma unroll
            for (int i = o - 8; i < o; i += 2) asm volatile("lop3.b32 %0, %0, %1, %2, 0x80;" : "+r"(keep) : "r"(hp[i]), "r"(hp[i + 1]));
        }
    }
}

__device__ __forceinline__ int pos_of(int n) { return (n & 24) + 4 * (n & 1) + ((n >> 1) & 3); }
__device__ __forceinline__ int unit_of(int role, int u, int& slot) {
    const int g = role & 7, w = (role >> 3) & 3, b = role >> 5;
    slot = role >= 128 ? g : (g ? 16 * g + w + 4 * b : 4 * w + b);
    return role >= 128 ? 32 * max(2 * g + u, 1) : (g ? g + 16 * w : ((w & 1) << 4) + ((w & 2) << 2)) + 64 * b + 256 * u;
}
template <int STRIDE> __device__ __forceinline__ bool tags_ok(uint32_t a, uint32_t ep) {
    uint32_t v[4], ok;
#pragma unroll
    for (int i = 0; i < 4; i++) asm volatile("ld.shared.u32 %0, [%1];" : "=r"(v[i]) : "r"(a + i * STRIDE) : "memory");
    asm volatile("{.reg .pred p; .reg .b32 a, b; lop3.b32 a, %1, %2, %5, 0x7e; lop3.b32 b, %3, %4, %5, 0x7e; lop3.b32 a, a, b, 1, 0xa8;\n"
                 "setp.eq.u32 p, a, 0; vote.sync.all.pred p, p, -1; selp.u32 %0, 1, 0, p;}" : "=r"(ok) : "r"(v[0]), "r"(v[1]), "r"(v[2]), "r"(v[3]), "r"(ep));
    return ok;
}
__device__ __forceinline__ void load_w_rows(uint32_t dst, const CUtensorMap* mr, const CUtensorMap* mi, int kap, uint32_t bar) {
    mbar_expect_tx(bar, 16 * WPITCH);
#pragma unroll 1
    for (int i = 0; i < 2; i++, dst += 8 * WPITCH, kap = (512 - kap) & 511) {
        tma2d(dst, mr, (kap * 1026 >> 4) * 2, 0, bar);
        tma2d(dst + 4 * WPITCH, mi, (kap * 1026 >> 4) * 2, 0, bar);
    }
}
__device__ __forceinline__ void prefetch_w_rows(const CUtensorMap* mr, const CUtensorMap* mi, int kap) {
#pragma unroll 1
    for (int i = 0; i < 2; i++, kap = (512 - kap) & 511) {
        asm volatile("cp.async.bulk.prefetch.tensor.2d.L2.global [%0, {%1,%2}];" ::"l"(mr), "r"((kap * 1026 >> 4) * 2), "r"(0) : "memory");
        asm volatile("cp.async.bulk.prefetch.tensor.2d.L2.global [%0, {%1,%2}];" ::"l"(mi), "r"((kap * 1026 >> 4) * 2), "r"(0) : "memory");
    }
}
template <int K0, int K1> __device__ __forceinline__ void store_v(const uint32_t (&vo)[32], const uint8_t* vp, bool p) {
    if (p) {
#pragma unroll
        for (int k = K0; k < K1; k++)
            asm volatile("st.global.v2.b32 [%0], {%1,%2};" ::"l"(vp + (k >> 2) * (1 << 20) + ((k >> 1) & 1) * 8192 + (k & 1) * (4 * 32768)), "r"(vo[2 * k]), "r"(vo[2 * k + 1]) : "memory");
    }
}
#define SB0 1024
__device__ __forceinline__ uint64_t ring_desc(uint32_t sb, uint32_t off, uint32_t lbo, uint32_t swz) {
    uint64_t d;
    asm volatile("{.reg .b32 z; shr.u32 z, %1, 28; mov.b64 %0, {z, z}; add.u64 %0, %0, %2;}" : "=l"(d) : "r"(sb), "l"(mkdesc(SB0 + off, lbo, 1024, swz)));
    return d;
}
struct Ring {
    uint32_t full, rel;
    uint32_t n;
    bool sig;
};
__device__ __forceinline__ void ring_release(const Ring& r, uint32_t o) {
    if (r.sig) asm volatile("mbarrier.arrive.shared::cluster.b64 _, [%0];" ::"r"(r.rel + o) : "memory");
}
__device__ __forceinline__ void peek(uint32_t a, uint32_t ph) { asm volatile("mbarrier.test_wait.parity.shared::cta.b64 pk, [%0], %1;" ::"r"(a), "r"(ph) : "memory"); }
__device__ __forceinline__ void peek_wait(uint32_t a, uint32_t ph, uint32_t& n) {
    asm volatile("{@pk bra DONE;\n"
                 "LOOP: mbarrier.try_wait.parity.shared::cta.b64 pk, [%1], %2; add.u32 %0, %0, 1; setp.gt.or.u32 pk, %0, %3, pk; @!pk bra LOOP;\n"
                 "DONE: }" : "+r"(n) : "r"(a), "r"(ph), "n"(SPIN_LIMIT) : "memory");
}
#define SL(k) ((k) % NST)
#define PH(k) (((k) / NST) & 1)
#define H64 "%64,%65,%66,%67,%68,%69,%70,%71,%72,%73,%74,%75,%76,%77,%78,%79,%80,%81,%82,%83,%84,%85,%86,%87,%88,%89,%90,%91,%92,%93,%94,%95," \
            "%96,%97,%98,%99,%100,%101,%102,%103,%104,%105,%106,%107,%108,%109,%110,%111,%112,%113,%114,%115,%116,%117,%118,%119,%120,%121,%122,%123,%124,%125,%126,%127"
#define WG_MMA "wgmma.mma_async.sync.aligned.m64n128k16.f32.bf16.bf16 "
#define DESC_B(S, j) "mov.b64 {t, hb}, %130; mov.b64 db, {%137 + 2048 * " #S " + 2 * " #j ", hb};\n"
#define MMA_LO(S, j, p) "add.u64 da, %129, 2048 * " #S " + %136 * " #j ";" DESC_B(S, j) WG_MMA "{" L64 "}, da, db, " #p ", 1, 1, %138, 0;\n"
#define MMA_HI(S, j, p) "add.u64 da, %129, 2048 * " #S " + 512 + %136 * " #j ";\n" WG_MMA "{" H64 "}, da, db, " #p ", 1, 1, %138, 0;\n"
#define STEP(S, P, N, ph, pa, pr, X, Y) \
    "wgmma.fence.sync.aligned;\n" MMA_LO(S, 0, pa) MMA_HI(S, 0, pa) \
    "wgmma.commit_group.sync.aligned; wgmma.wait_group.sync.aligned 1; @" #pr " mbarrier.arrive.shared::cluster.b64 _, [%132 + 8 * " #P "];\n" MMA_LO(S, 1, 1) \
    "mbarrier.test_wait.parity.shared::cta.b64 pk, [%131 + 8 * " #N "], " #ph ";\n" MMA_HI(S, 1, 1) MMA_LO(S, 2, 1) X MMA_HI(S, 2, 1) MMA_LO(S, 3, 1) MMA_HI(S, 3, 1) \
    "wgmma.commit_group.sync.aligned;\n" P4A Y "@pk bra GO" #S ";\n" \
    "WAIT" #S ": mbarrier.try_wait.parity.shared::cta.b64 pk, [%131 + 8 * " #N "], " #ph "; add.u32 %128, %128, 1; setp.gt.or.u32 pk, %128, %139, pk; @!pk bra WAIT" #S ";\n" \
    "GO" #S ":\n" P4B
#define P4A
#define P4B
#define P4I
#define P4O
#define STEP_ARGS(TA) \
    : R8(d, 0), R8(d, 8), R8(d, 16), R8(d, 24), R8(d, 32), R8(d, 40), R8(d, 48), R8(d, 56), \
      R8(d, 64), R8(d, 72), R8(d, 80), R8(d, 88), R8(d, 96), R8(d, 104), R8(d, 112), R8(d, 120), "+r"(r.n) \
    : "l"(ha), "l"(hb), "r"(r.full), "r"(r.rel), "r"((uint32_t)r.sig), "r"(wg), \
      "n"(SB0 / 16 + (TA ? 32 << 16 : 1 << 16)), "n"(TA ? 128 : 2), "n"(SB0 / 16 + 1024 + (1 << 16)), "n"(TA), "n"(SPIN_LIMIT) P4O \
    : "memory"
#define STEP_REGS "{.reg .b32 k, t, ph, hb; .reg .b64 da, db; .reg .pred ps, pl, pa, pr;\n" P4I "setp.ne.u32 ps, %133, 0;\n"
#define FIRST_WAIT "FIRST: mbarrier.try_wait.parity.shared::cta.b64 pk, [t], ph; @pk bra START; add.u32 %128, %128, 1; setp.le.u32 pk, %128, %139; @pk bra FIRST; START:\n"
__device__ __forceinline__ void gemm1(float (&d)[128], Ring& r, uint64_t ha, uint64_t hb, int wg) {
    asm volatile(STEP_REGS "mul.lo.u32 k, %134, 15; mov.b32 ph, %134; setp.ne.u32 pl, k, 0; mad.lo.u32 t, %134, 8, %131;\n"
                 "pmevent 1; @pl bar.sync 1, 256;\n" FIRST_WAIT "@pl bra ONE;\n"
                 "LOOP: setp.ne.u32 pa, k, 0; and.pred pr, pa, ps; setp.eq.u32 pl, k, 15;\n"
                 STEP(0, 4, 1, ph, pa, pr, "@pl bar.arrive 1, 256;\n", "@pl bra END;\n")
                 "ONE: setp.ne.u32 pa, k, 15; and.pred pr, pa, ps; setp.eq.u32 pl, k, 30;\n"
                 STEP(1, 0, 2, ph, pa, pr, "@pl bar.arrive 2, 256;\n", "@pl bra END;\n")
                 STEP(2, 1, 3, ph, 1, ps, "", "") STEP(3, 2, 4, ph, 1, ps, "", "") "xor.b32 ph, ph, 1; add.u32 k, k, 5;\n" STEP(4, 3, 0, ph, 1, ps, "", "")
                 "bra LOOP;\n"
                 "END:\n" P4B "}" STEP_ARGS(0));
}
__device__ __forceinline__ void gemm2(float (&d)[128], Ring& r, uint64_t ha, uint64_t hb, int wg) {
    asm volatile(STEP_REGS "mov.b32 k, 0; mov.b32 ph, 0; add.u32 t, %131, 16;\n"
                 "pmevent 1; bar.sync 2, 256;\n" FIRST_WAIT
                 "LOOP: setp.ne.u32 pa, k, 0; and.pred pr, pa, ps; setp.eq.u32 pl, k, 5;\n"
                 STEP(2, 1, 3, ph, pa, pr, "", "") STEP(3, 2, 4, ph, 1, ps, "", "") "xor.b32 ph, ph, 1; add.u32 k, k, 1;\n" STEP(4, 3, 0, ph, 1, ps, "", "")
                 "@pl bra END;\n" STEP(0, 4, 1, ph, 1, ps, "", "") STEP(1, 0, 2, ph, 1, ps, "", "")
                 "bra LOOP;\n"
                 "END: }" STEP_ARGS(1));
}
template <int O, int K, int J> __device__ __forceinline__ void mma_h(float (&y)[128], uint64_t a, uint64_t b) { mma128_ss<O, 1, 0>(y, a + SL(K) * 2048 + O * 8 + 128 * J, b + SL(K) * 2048 + 2 * J, 1); }
template <int O, int K> __device__ __forceinline__ void half_step(float (&y)[128], uint64_t a, uint64_t b) { mma_h<O, K, 0>(y, a, b); mma_h<O, K, 1>(y, a, b); mma_h<O, K, 2>(y, a, b); mma_h<O, K, 3>(y, a, b); }
template <int R, int U> __device__ __forceinline__ void out_piece(float (&y)[128], const uint32_t (&dd)[16], uint32_t x0, uint32_t x1, float* op) {
    const int i = 64 * (R >> 1) + 8 * U + 2 * (R & 1);
    asm("mul.rn.bf16x2 %0, %0, %1;" : "+r"(x0) : "r"(dd[2 * U]));
    asm("mul.rn.bf16x2 %0, %0, %1;" : "+r"(x1) : "r"(dd[2 * U + 1]));
    asm volatile("st.global.v4.f32 [%0], {%1,%2,%3,%4};" ::"l"(op + (32 * (R & 1) + 16 * (R >> 1)) * 2048 + 16 * U),
                 "f"(y[i] + __uint_as_float(x0 << 16)), "f"(y[i + 1] + __uint_as_float(x0 & 0xffff0000u)),
                 "f"(y[i + 4] + __uint_as_float(x1 << 16)), "f"(y[i + 5] + __uint_as_float(x1 & 0xffff0000u)) : "memory");
}
template <int R, int U0> __device__ __forceinline__ void load_x4(uint32_t (&xx)[8], uint32_t xa) {
#pragma unroll
    for (int u = 0; u < 4; u++)
        asm volatile("ld.shared.v2.b32 {%0,%1}, [%2];" : "=r"(xx[2 * u]), "=r"(xx[2 * u + 1]) : "r"((xa ^ (u << 5)) + (3 - R) * 8192 + U0 * 1024) : "memory");
}
__device__ __forceinline__ Ring ring_at(uint32_t sb, int k) {
    Ring r;
    r.n = 0;
    r.full = sb + OFF_BAR + B_FULL;
    asm("mapa.shared::cluster.u32 %0, %1, %2;" : "=r"(r.rel) : "r"(sb + OFF_BAR + B_EMPTY), "r"((threadIdx.x >> 5) & 1));
    r.sig = __shfl_sync(~0u, threadIdx.x & 95, threadIdx.x) == 0;
    return r;
}

template <bool BY_SM> __global__ void __cluster_dims__(2, 1, 1) __launch_bounds__(512, 1)
fused_kernel(const __grid_constant__ CUtensorMap tmX, const __grid_constant__ CUtensorMap tmBre, const __grid_constant__ CUtensorMap tmBim,
             const __grid_constant__ CUtensorMap tmCre, const __grid_constant__ CUtensorMap tmCim, const __grid_constant__ CUtensorMap tmXd,
             const __grid_constant__ CUtensorMap tmUst, const __grid_constant__ CUtensorMap tmVst,
             const __grid_constant__ CUtensorMap tmWr, const __grid_constant__ CUtensorMap tmWi, const __grid_constant__ CUtensorMap tmXa,
             const Params p) {
    extern __shared__ __align__(1024) uint8_t smraw[];
    asm volatile(".reg .pred pk, p0;");
    const int tid = threadIdx.x, rank = blockIdx.x & 1;
    const uint32_t wi = __shfl_sync(~0u, smem_u32(smraw) + (tid >> 5), 0), sb = wi & ~15u, bars = sb + OFF_BAR;
    const int wg = (wi >> 2) & 3, w = wi & 3, lane = tid & 31, g = lane >> 2, q = lane & 3;
    if (wg != 3) asm volatile("barrier.cluster.arrive.relaxed.aligned; barrier.cluster.wait.aligned;" ::: "memory");
    else asm volatile("prefetch.tensormap [%0];" ::"l"(w == 0 ? &tmX : w == 1 ? &tmBre : &tmBim) : "memory");
    int role;
    {
        uint32_t T = blockIdx.x;
        if (BY_SM) asm("mov.u32 %0, %%smid;" : "=r"(T));
        T >>= 1;
        const uint32_t a = ((T - 32) * 37) >> 8;
        asm("{.reg .pred p; setp.lt.u32 p, %1, 62; selp.u32 %0, 4, -58, p; add.u32 %0, %0, %1;\n"
            "setp.lt.u32 p, %1, 60; selp.u32 %0, %2, %0, p; setp.lt.u32 p, %1, 32; selp.u32 %0, %3, %0, p;}"
            : "=&r"(role) : "r"(T), "r"(8 * (T - 31 - 7 * a) + 4 + a), "r"(8 * (T & 7) + (T >> 3)));
        role = 2 * role + rank;
    }
    const bool spare = role >= 128;
    const int tc = ((role >> 3) & 14) + rank, cb = (role >> 1) & 7;
    const int fb = role >> 5, fcb = role & 31, fpos = pos_of(fcb);
    const int nu = role == 128 ? 1 : (fcb || !role ? 2 : 0);

    if (wg == 3) {
        if (elect_one()) {
            const uint32_t b = bars + w * 8;
            STAMP5(57);
            mbar_init(b, 1);
            if (w < 3 && !spare) {
                mbar_expect_tx(b, 32768);
                tma5d(sb + w * 32768 + 16384, &tmX, w * 64, 0, 0, 0, tc, b);
                if (w == 0) { tma4d(sb, &tmBre, 0, 0, 0, cb * 4, b); tma4d(sb + 8192, &tmBim, 0, 0, 0, cb * 4, b); }
                STAMP5(58);
            }
#pragma unroll
            for (int o = 32; o < B_EPOCH; o += 32) mbar_init(b + o, o < B_EMPTY ? 1 : (o < B_STG ? 2 : (o < B_P3M ? 4 : 8)));
            asm volatile("fence.mbarrier_init.release.cluster;" ::: "memory");
        }
        __syncwarp();
        STAMP5(59);
        asm volatile("barrier.cluster.arrive.relaxed.aligned;" ::: "memory");
    }
    if (opaque32(wg) == 3) {
        asm volatile("setmaxnreg.dec.sync.aligned.u32 24;");
        asm volatile("barrier.cluster.wait.aligned;" ::: "memory");
        if (w == 0) {
            if (!spare && elect_one()) {
                STAMP(56);
#pragma unroll 1
                for (int k = 1; k < NST; k++) {
                    if (k >= 3) mbar_expect_tx(bars + B_FULL + k * 8, 32768);
                    tma4d_mc(sb + k * 32768 + rank * 8192, rank ? &tmBim : &tmBre, k * 64, 0, 0, cb * 4, bars + B_FULL + k * 8);
                    if (k >= 3) tma5d(sb + k * 32768 + 16384, &tmX, k * 64, 0, 0, 0, tc, bars + B_FULL + k * 8);
                }
#define RING_WAIT "mbarrier.try_wait.parity.shared::cta.b64 p, [fb + 256], ph; @p bra GO;\n" \
                  "WAIT: mbarrier.try_wait.parity.shared::cta.b64 p, [fb + 256], ph; add.u32 n, n, 1; setp.gt.or.u32 p, n, 32768, p; @!p bra WAIT;\nGO:\n"
#define RING_NEXT "pmevent 1; add.u32 o, o, 8; setp.eq.u32 p, o, 40; selp.u32 o, 0, o, p; @p xor.b32 ph, ph, 1; add.u32 fb, %1, o; shl.b32 t, o, 12; add.u32 da, %0, t;\n"
                asm volatile("{.reg .b32 o, k, kk, c2, da, db, fb, ph, n, t; .reg .pred p;\n"
                             "mov.b32 o, 0; mov.b32 k, 320; mov.b32 kk, 320; mov.b32 c2, 0; mov.b32 ph, 0; mov.b32 n, 0; mov.b32 fb, %1; mov.b32 da, %0; mov.b32 db, %2;\n"
                             "LOOP:\n" RING_WAIT
                             "cp.async.bulk.tensor.5d.shared::cluster.global.mbarrier::complete_tx::bytes [da], [%3, {kk,0,0,0,%5}], [fb];\n"
                             "cp.async.bulk.tensor.4d.shared::cluster.global.mbarrier::complete_tx::bytes.multicast::cluster [db], [%4, {kk,0,c2,%6}], [fb], %7;\n"
                             "mbarrier.arrive.expect_tx.shared::cta.b64 _, [fb], 32768;\n" RING_NEXT
                             "add.u32 db, %2, t; add.u32 k, k, 64; and.b32 kk, k, 1023; shr.u32 c2, k, 9; and.b32 c2, c2, 2; setp.ne.u32 p, k, 2048; @p bra LOOP;}"
                             ::"r"(sb + 16384), "r"(bars + B_FULL), "r"(sb + rank * 8192), "l"(&tmX), "l"(rank ? &tmBim : &tmBre), "r"(tc), "r"(cb * 4), "h"((uint16_t)3) : "memory");
                asm volatile("{.reg .b32 o, k, kk, da, db, fb, hb, ph, n, t; .reg .b64 m, src; .reg .pred p;\n"
                             "mov.b32 o, 16; mov.b32 k, 0; mov.b32 kk, 0; mov.b32 ph, 1; mov.b32 n, 0; add.u32 fb, %1, 16; add.u32 hb, %1, 72; add.u32 da, %0, 65536; add.u32 db, %2, 65536;\n"
                             "mov.b64 m, %3; mov.b64 src, %5;\n"
                             "GROUP: add.u32 t, %8, k;\n"
                             "OWN: mbarrier.try_wait.parity.shared::cta.b64 p, [t], 0; add.u32 n, n, 1; setp.gt.or.u32 p, n, 32768, p; @!p bra OWN;\n"
                             "LOOP:\n" RING_WAIT
                             "cp.async.bulk.shared::cluster.global.mbarrier::complete_tx::bytes [da], [src], 16384, [hb];\n"
                             "cp.async.bulk.tensor.5d.shared::cluster.global.mbarrier::complete_tx::bytes.multicast::cluster [db], [m, {kk,0,0,0,%6}], [fb], %7;\n"
                             "mbarrier.expect_tx.shared::cta.b64 [fb], 16384; mbarrier.arrive.expect_tx.shared::cta.b64 _, [hb], 16384;\n" RING_NEXT
                             "add.u32 db, %2, t; add.u64 src, src, 16384; sub.u64 m, %4, m; add.u32 k, k, 1; shl.b32 kk, k, 5; and.b32 kk, kk, 0x7c0;\n"
                             "and.b32 t, k, 1; mad.lo.u32 hb, t, 8, fb; add.u32 hb, hb, o; add.u32 hb, hb, 40;\n"
                             "and.b32 t, k, 7; setp.ne.u32 p, t, 0; @p bra LOOP; setp.ne.u32 p, k, 32; @p bra GROUP;}"
                             ::"r"(sb), "r"(bars + B_FULL), "r"(sb + 16384 + rank * 8192), "l"(&tmCre), "l"((uint64_t)&tmCre + (uint64_t)&tmCim),
                               "l"(g_H + (size_t)tc * 32 * 16384), "r"(cb * 8 + rank * 4), "h"((uint16_t)3), "r"(bars + B_HOWN) : "memory");
            }
        } else if (opaque32(w) == 1) {
            const unsigned ep = ld_rlx(g_epoch + role * 8) + 1;
            __syncwarp();
            if (elect_one()) {
                asm volatile("st.relaxed.gpu.global.u32 [%0], %1;" ::"l"(g_epoch + role * 8), "r"(ep) : "memory");
                asm volatile("st.shared.u32 [%0], %1;" ::"r"(bars + B_EPOCH), "r"(ep) : "memory");
                mbar_arrive(bars + B_EP);
            }
            int slot;
            const int kap = unit_of(role, 0, slot), kap1 = unit_of(role, 1, slot);
            uint32_t lph = 0;
            if (!spare) mbar_wait(bars + B_STGU, 0);
            STAMP(21);
            const int c0 = fb * 2048 + fpos * 64;
            if (elect_one()) {
                if (!spare) {
#pragma unroll 1
                    for (int r = 4; r < 8; r++) bulk_st(g_X + r * (32 * 16384) + c0 * 2, sb + OFF_P + r * 4096, 128);
                    tma2d_st(&tmUst, c0, 0, sb + OFF_P);
                    bulk_commit();
                    tma2d_st(&tmUst, c0, 64, sb + OFF_P + 8192);
                    bulk_commit();
                    asm volatile("cp.async.bulk.wait_group.read 1;" ::: "memory");
                    red_hint(g_cnt);
                }
                mbar_expect_tx(bars + B_FG, 8192);
                bulk_ld(sb + OFF_F, (const uint8_t*)g_tab + TAB_FG, 8192, bars + B_FG);
            }
            STAMP(40);
#pragma unroll 1
            for (int e = 0; e < 4; e++) {
                if (e >= 2) {
                    if (e == nu) {
                        mbar_wait(bars + B_WFREE, 0);
                        if (elect_one()) load_w_rows(sb + OFF_WD, &tmWr, &tmWi, kap1, bars + B_WD);
                    }
                    if (e - 2 < nu) mbar_wait(bars + B_STG, e & 1);
                    STAMPO(23, e - 2);
                    if (e == nu && elect_one()) {
                        const int c = (role ? slot : 256) * 32;
                        tma2d_st(&tmVst, c, 0, sb + OFF_P);
                        tma2d_st(&tmVst, c + 4096, 0, sb + OFF_P + 8192);
                        bulk_commit();
                        if (role) { bulk_wait_read(); red_hint(g_cnt + 64); } else bulk_wait_all();
                    }
                    if (e == 3 && !spare && elect_one()) {
                        mbar_expect_tx(bars + B_FG, 8192);
                        bulk_ld(sb + OFF_F, (const uint8_t*)g_tab + TAB_G + fb * 8192, 8192, bars + B_FG);
                    }
                }
                const uint32_t tg = e < 2 ? lane * 128 + ((((lane >> 1) & 2) ^ (lane & 3)) << 4) + (lane >> 3) * 4 : lane * 64 + (lane & 8) * 4 + (lane & 2) * 8 + (lane & 4) * 2;
                if (spare) {
                    if (e == 1) {
                        wait_cnt(g_cnt, 128 * ep);
                        STAMP(42);
#pragma unroll 1
                        for (int n = 0; n < 4096; n++) {
                            if (elect_one()) {
                                mbar_expect_tx(bars + B_LD, 8 * 16384);
#pragma unroll 1
                                for (int r = 0; r < 8; r++) bulk_ld(sb + r * 16384, g_X + (size_t)r * (32 * 16384), 16384, bars + B_LD);
                            }
                            mbar_wait(bars + B_LD, n & 1);
                            bool ok = true;
#pragma unroll 1
                            for (int r = 0; r < 8; r++) ok &= tags_ok<4096>(sb + r * 16384 + tg, ep);
                            if (ok) break;
                        }
                        if (elect_one()) mbar_arrive(bars + B_RAW);
                    }
                } else {
                    const uint32_t dst = sb + OFF_P + (e & 1) * 16384;
#define X_ST1
#define X_ST2
#define X_RETRY
#define X_ARG
                    asm volatile("{.reg .b32 n, a, v0, v1, v2, v3; .reg .pred p, pe, pu;\n"
                                 "elect.sync _|pe, 0xffffffff; setp.lt.u32 pu, %10, 2; mov.b32 n, 0; pmevent 1;\n"
                                 "POLL: ld.relaxed.gpu.global.u32 v0, [%1]; setp.eq.u32 p, v0, %2; @p bra LOAD;\n"
                                 "nanosleep.u32 20; add.u32 n, n, 1; setp.lt.u32 p, n, 32768; @p bra POLL;\n"
                                 "LOAD:\n" X_ST1 "cp.async.bulk.wait_group.read 0;\n"
                                 "@pe cp.async.bulk.shared::cluster.global.mbarrier::complete_tx::bytes [%3], [%4], 16384, [%5]; @pe mbarrier.arrive.expect_tx.shared::cta.b64 _, [%5], 16384;\n"
                                 "mov.b32 a, 0;\n"
                                 "WAIT: mbarrier.try_wait.parity.shared::cta.b64 p, [%5], %0; @p bra CHECK; add.u32 n, n, 1; setp.lt.u32 p, n, 65536; @p bra WAIT;\n"
                                 "CHECK:\n" X_ST2 "@pu bra FOUR;\n"
                                 "ld.shared.u32 a, [%7]; ld.shared.u32 v0, [%6 + 2048]; ld.shared.u32 v1, [%6 + 6144]; ld.shared.u32 v2, [%6 + 10240]; ld.shared.u32 v3, [%6 + 14336];\n"
                                 "lop3.b32 a, a, v0, %8, 0x7e; lop3.b32 v1, v1, v2, %8, 0x7e; lop3.b32 a, a, v3, %8, 0xf6; or.b32 a, a, v1;\n"
                                 "FOUR: ld.shared.u32 v0, [%6]; ld.shared.u32 v1, [%6 + 4096]; ld.shared.u32 v2, [%6 + 8192]; ld.shared.u32 v3, [%6 + 12288];\n"
                                 "lop3.b32 a, a, v0, %8, 0xf6; lop3.b32 a, a, v1, %8, 0xf6; lop3.b32 v2, v2, v3, %8, 0x7e; lop3.b32 a, a, v2, 1, 0xa8;\n"
                                 "setp.eq.u32 p, a, 0; vote.sync.all.pred p, p, -1; @p bra OK;\n" X_RETRY
                                 "add.u32 n, n, 16; setp.ge.u32 p, n, 65536; @p bra OK; xor.b32 %0, %0, 1; bra LOAD;\n"
                                 "OK: @pe mbarrier.arrive.shared::cta.b64 _, [%9]; pmevent 1; xor.b32 %0, %0, 1;}"
                                 : "+r"(lph)
                                 : "l"(g_cnt + e * 32), "r"(128 * ep), "r"(dst), "l"(g_X + (size_t)(e < 2 ? role + e * 128 : 254 + (fb * 32 + fpos) * 2 + e) * 16384), "r"(bars + B_LD),
                                   "r"(dst + tg), "r"(dst + (e == 3 ? (lane & 1) * 8192 + 32 : 0)), "r"(ep), "r"(bars + B_IN + e * 8), "r"(e) X_ARG : "memory");
                }
                if (e < 2 && elect_one()) {
                    if (e) prefetch_w_rows(&tmWr, &tmWi, kap1);
                    else {
                        if (nu) load_w_rows(sb + OFF_WD, &tmWr, &tmWi, kap, bars + B_WD);
                        if (!spare) {
                            tma2d_st(&tmUst, c0, 128, sb + OFF_P + 16384);
                            tma2d_st(&tmUst, c0, 192, sb + OFF_P + 24576);
                            bulk_commit();
                            bulk_wait_read();
                            red_hint(g_cnt + 32);
                        }
                    }
                }
            }
            if (!spare) {
                mbar_wait(bars + B_HOWN + 8, 0);
#pragma unroll 1
                for (int r = 0; r < 4; r++) {
                    if (r == 3) mbar_wait(bars + B_P3M, 0);
                    if (elect_one()) {
                        if (r == 0) { mbar_expect_tx(bars + B_XD, 24576 + 256); mbar_expect_tx(bars + B_XD + 8, 8192); bulk_ld(sb + OFF_LAM, p.dsk + cb * 128, 256, bars + B_XD); }
                        tma4d(sb + OFF_F + (3 - r) * 8192, &tmXd, 0, tc * 128 + 32 * (r & 1) + 16 * (r >> 1), 0, cb * 2, bars + B_XD + (r == 3) * 8);
                    }
                    __nanosleep(PACE_X);
                }
            }
        } else {
            if (w == 2) {
                {
                    const int u = lane >> 4;
                    int slot;
                    const int r0 = unit_of(role, u, slot) + 512 * ((lane >> 1) & 3), r1 = (2048 - r0) & 2047, mir = (lane >> 3) & 1;
                    const unsigned short* wp = (const unsigned short*)((lane & 1) ? p.wi : p.wr);
                    const float a = bf2f(wp[r0 * 513 + mir * 512]), b = bf2f(wp[r1 * 513 + mir * 512]);
                    asm volatile("st.shared.f32 [%0], %1;" ::"r"(sb + OFF_WSP + u * 64 + (lane & 15) * 4), "f"(0.5f * ((lane & 1) ? (mir ? b - a : a - b) : a + b)) : "memory");
                }
                warp_arrive(bars + B_WSP);
            } else if (!spare) {
#pragma unroll 1
                for (int i = 0; i < 8; i++) {
                    if (i >= XA_N0) __nanosleep(XA_PACE);
                    if (elect_one()) {
                        const uint32_t xb = bars + (i < 4 ? B_RAW : B_XIN);
                        if (!(i & 3)) mbar_expect_tx(xb, 16384);
                        tma3d(sb + OFF_F + i * 4096, &tmXa, fcb * 32, 0, 4 * i + fb, xb);
                    }
                }
            }
            if (!spare) {
                if (w == 2 && nu) {
                    int slot;
                    const int kap = unit_of(role, 0, slot);
                    mbar_wait(bars + B_XIN, 0);
                    if (elect_one()) prefetch_w_rows(&tmWr, &tmWi, kap);
                }
                const unsigned ep = get_epoch(bars);
#define CNT_RETRY
#define CNT_ARG
                asm volatile("{.reg .b32 o, k, hb, fb, ca, m, ph, rph, n, t, v0, v1, v2, v3; .reg .b64 src; .reg .pred p, pe;\n"
                             "elect.sync _|pe, 0xffffffff; mov.b32 o, %0; shr.u32 k, %0, 3; sub.u32 k, k, 2; mov.b32 m, 0x107c0; mov.b32 rph, 0; mov.b32 n, 0;\n"
                             "bra NEXT;\n"
                             "LOOP: mbarrier.try_wait.parity.shared::cta.b64 p, [hb], ph; @p bra GO;\n"
                             "WAIT: mbarrier.try_wait.parity.shared::cta.b64 p, [hb], ph; add.u32 n, n, 1; setp.gt.or.u32 p, n, 32768, p; @!p bra WAIT;\n"
                             "GO: ld.shared.u32 v0, [ca]; ld.shared.u32 v1, [ca + 128]; ld.shared.u32 v2, [ca + 256]; ld.shared.u32 v3, [ca + 384];\n"
                             "lop3.b32 v0, v0, v1, %4, 0x7e; lop3.b32 v2, v2, v3, %4, 0x7e; lop3.b32 v0, v0, v2, 1, 0xa8; setp.eq.u32 p, v0, 0; vote.sync.all.pred p, p, -1; @p bra OK;\n"
                             CNT_RETRY "add.u32 n, n, 16; setp.gt.u32 p, n, 32768; @p bra OK;\n"
                             "shl.b32 t, o, 12; add.u32 t, t, %5; mad.wide.u32 src, k, 16384, %6;\n"
                             "@pe mbarrier.arrive.expect_tx.shared::cta.b64 _, [%7], 16384; @pe cp.async.bulk.shared::cluster.global.mbarrier::complete_tx::bytes [t], [src], 16384, [%7];\n"
                             "AGAIN: mbarrier.try_wait.parity.shared::cta.b64 p, [%7], rph; add.u32 n, n, 1; setp.gt.or.u32 p, n, 32768, p; @!p bra AGAIN;\n"
                             "xor.b32 rph, rph, 1; bra GO;\n"
                             "OK: @pe mbarrier.arrive.shared::cta.b64 _, [fb]; pmevent 1;\n"
                             "add.u32 o, o, 16; setp.ge.u32 p, o, 40; @p sub.u32 o, o, 40; add.u32 k, k, 2;\n"
                             "NEXT: shr.u32 m, m, 1; and.b32 ph, m, 1; add.u32 fb, %1, o; mad.lo.u32 hb, o, 2, %2; mad.lo.u32 ca, o, 4096, %3; setp.lt.u32 p, k, 32; @p bra LOOP;}"
                             ::"r"(8 * w), "r"(bars + B_FULL), "r"(bars + B_HL - 16 + w * 8), "r"(sb + (q >> 1) * 8192 + (q & 1) * 512 + g * 1040 + q * 4), "r"(ep),
                               "r"(sb), "l"(g_H + (size_t)tc * 32 * 16384), "r"(bars + B_HR - 16 + w * 8) CNT_ARG : "memory");
                if (w == 3) warp_arrive(bars + B_DONE);
            }
        }
    } else {
        STAMP(55);
        asm volatile("setmaxnreg.inc.sync.aligned.u32 152;");
        STAMP5(60);
        const int t7 = tid & 127, hf = wg - 1;
        const int mi = lane >> 3, gl = lane & 7;
        if (spare && wg != 2) {
            if (tid < 64) { const uint4 v = __ldg((const uint4*)((const uint8_t*)g_tab + TAB_PC) + tid); sts128(sb + OFF_LAM + tid * 16, v.x, v.y, v.z, v.w); }
            bar_sync(1, 256);
            mbar_wait(bars + B_RAW, 0);
            STAMP(0);
#pragma unroll 1
            for (int u = 0; u < nu; u++) {
                int slot;
                const int t = unit_of(role, u, slot) >> 5;
                const uint32_t off = (tid >> 2) * 128 + q * 16;
                float zr[16], zi[16];
#pragma unroll
                for (int k = 0; k < 16; k++) zr[k] = zi[k] = 0.f;
#pragma unroll 1
                for (int r = (t & 1) ? 0 : t >> 1; r < 8 - ((t & 1) ? 0 : (t >> 1) - 1); r += (t & 1) ? 1 : 8 - t) {
                    float4 c;
                    float a[8], b[8];
                    lds128f(sb + OFF_LAM + t * 128 + r * 16, c.x, c.y, c.z, c.w);
                    lds128f(sb + r * 16384 + off, a[0], a[1], a[2], a[3]);
                    lds128f(sb + r * 16384 + off + 64, b[0], b[1], b[2], b[3]);
                    lds128f(sb + r * 16384 + off + 8192, a[4], a[5], a[6], a[7]);
                    lds128f(sb + r * 16384 + off + 8192 + 64, b[4], b[5], b[6], b[7]);
#pragma unroll
                    for (int k = 0; k < 16; k++) {
                        const uint32_t ua = __float_as_uint(a[k >> 1]), ub = __float_as_uint(b[k >> 1]);
                        const float x = __uint_as_float((k & 1) ? ua & 0xffff0000u : ua << 16), y = __uint_as_float((k & 1) ? ub & 0xffff0000u : ub << 16);
                        zr[k] = fmaf(c.x, x, fmaf(c.z, y, zr[k]));
                        zi[k] = fmaf(c.y, x, fmaf(c.w, y, zi[k]));
                    }
                }
                const uint32_t dst = sb + OFF_P + u * 16384 + off;
#pragma unroll
                for (int k = 0; k < 16; k += 8) {
                    sts128(dst + k * 1024, pk(zr[k], zr[k + 1]), pk(zr[k + 2], zr[k + 3]), pk(zr[k + 4], zr[k + 5]), pk(zr[k + 6], zr[k + 7]));
                    sts128(dst + k * 1024 + 64, pk(zi[k], zi[k + 1]), pk(zi[k + 2], zi[k + 3]), pk(zi[k + 4], zi[k + 5]), pk(zi[k + 6], zi[k + 7]));
                }
                fence_async_sm();
                bar_sync(1, 256);
                if (tid == 0) mbar_arrive(bars + B_IN + u * 8);
                STAMPO(1, u);
            }
            return;
        }
        if (wg == 2 && !spare) {
            asm volatile("setmaxnreg.inc.sync.aligned.u32 176;");
            uint32_t f1[16];
            cf tw[8];
            if (TAB_T0) __nanosleep(TAB_T0);
            ldtab<4, 2048>(f1, TAB_F1 + t7 * 16);
            ldtab_cf<16>(tw, TAB_TW1 + (t7 >> 2) * 64);
            const uint32_t ep = get_epoch(bars);
            uint32_t a0 = sb + OFF_P + (8 * w + gl + 32 * (mi >> 1)) * 128 + (((((mi & 1) << 2) | (fpos & 3)) ^ gl) << 4);
            float acc[128];
            const uint64_t dx = opaque(mkdesc(sb + OFF_F, 4096, 512, 2));
            mbar_wait(bars + B_RAW, 0);
            pinu(f1);
            wg_fence();
#pragma unroll
            for (int j = 0; j < 4; j++) mma128_rs<0, 1>(acc, f1[4 * j], f1[4 * j + 1], f1[4 * j + 2], f1[4 * j + 3], dx + j * 64, j);
            wg_commit();
            mbar_wait(bars + B_XIN, 0);
            wg_fence();
            STAMP(20);
#pragma unroll
            for (int j = 0; j < 4; j++) mma128_rs<64, 1>(acc, f1[4 * j], f1[4 * j + 1], f1[4 * j + 2], f1[4 * j + 3], dx + 1024 + j * 64, j);
            wg_commit();
            wg_wait<0>();
            pin(acc);
            pinu(f1);
#pragma unroll 1
            for (int h = 0;; h++) {
                const uint32_t tmask = 2 * q + h == fpos >> 2 ? ~1u : ~0u, tbit = ep & ~tmask;
#pragma unroll
                for (int cl = 0; cl < 2; cl++) {
                    c2 v[8];
#pragma unroll
                    for (int n = 0; n < 8; n++) {
                        const int i = 4 * (4 * n + cl);
                        v[n] = {{acc[i], acc[i + 2]}, {acc[i + 1], acc[i + 3]}};
                    }
                    dft8<true, YP1>(v, tw);
#pragma unroll
                    for (int r = 0; r < 8; r += 2) {
                        uint32_t o0 = pk(v[r].a.x, v[r].b.x), o1 = pk(v[r].a.y, v[r].b.y), o2 = pk(v[r + 1].a.x, v[r + 1].b.x), o3 = pk(v[r + 1].a.y, v[r + 1].b.y);
                        if (cl == 0) { o0 = (o0 & tmask) | tbit; o2 = (o2 & tmask) | tbit; }
                        stsm4((a0 ^ (cl << 4)) + r * 4096, o0, o1, o2, o3);
                    }
                }
                if (h) break;
                a0 ^= 32;
#pragma unroll
                for (int n = 0; n < 8; n++) {
                    asm volatile("mov.b32 %0, %8; mov.b32 %1, %9; mov.b32 %2, %10; mov.b32 %3, %11; mov.b32 %4, %12; mov.b32 %5, %13; mov.b32 %6, %14; mov.b32 %7, %15; pmevent 1;"
                                 : "=&f"(acc[16 * n]), "=&f"(acc[16 * n + 1]), "=&f"(acc[16 * n + 2]), "=&f"(acc[16 * n + 3]), "=&f"(acc[16 * n + 4]), "=&f"(acc[16 * n + 5]), "=&f"(acc[16 * n + 6]), "=&f"(acc[16 * n + 7])
                                 : "f"(acc[16 * n + 8]), "f"(acc[16 * n + 9]), "f"(acc[16 * n + 10]), "f"(acc[16 * n + 11]), "f"(acc[16 * n + 12]), "f"(acc[16 * n + 13]), "f"(acc[16 * n + 14]), "f"(acc[16 * n + 15]));
                }
            }
            fence_async_sm();
            warp_arrive(bars + B_STGU);
            bar_sync(3, 128);
            asm volatile("setmaxnreg.dec.sync.aligned.u32 152;");
            bar_arrive(7, 256);
        }
        if (wg == 1) {
            if (LAM_T0) __nanosleep(LAM_T0);
            const int cl = tid & 127, ch = (cl >> 6) * 512 + ((cl >> 3) & 1) * 256 + cb * 32 + ((cl >> 4) & 3) * 8 + (cl & 7);
            const float lr = bf2f(*(const unsigned short*)padd(p.lre, 2 * ch)), li = bf2f(*(const unsigned short*)padd(p.lim, 2 * ch));
            const float dt = __bfloat162float(__float2bfloat16(expf(bf2f(*(const unsigned short*)padd(p.ldt, 2 * ch)))));
            const float an = dt * li, th = an * 0.318309873342514f;
            float sn, cs, inv;
            sincospif(fmaf(rintf(0.5f * th), -2.f, th) + fmaf(an, 1.2841276653e-8f, fmaf(an, 0.318309873342514f, -th)), &sn, &cs);
            const float ex = expf(dt * lr), br = ex * cs, bi = ex * sn;
            asm("rcp.approx.f32 %0, %1;" : "=f"(inv) : "f"(lr * lr + li * li));
            inv += inv;
            const float cr = ((br - 1.f) * lr + bi * li) * inv, ci = (bi * lr - (br - 1.f) * li) * inv;
            sts128(sb + OFF_LAM + cl * 16, __float_as_uint(br), __float_as_uint(-bi), __float_as_uint(cr), __float_as_uint(-ci));
            mbar_wait(bars + B_EP, 0);
            bar_sync(8, 128);
            if (tid == 128) mbar_arrive(bars + B_LAM);
        }
        if (wg != 2) {
        if (wg == 0) bar_sync(4, 128); else bar_sync(7, 256);
        asm volatile("setmaxnreg.inc.sync.aligned.u32 160;");
        if (wg == 0) bar_sync(4, 128);
        float d[128];
        STAMPW(0, 10);
        Ring rg = ring_at(sb, role * 66 + wg * 16);
        cf lam[2];
        unsigned ep;
        gemm1(d, rg, ring_desc(sb, 0, 16, 1), ring_desc(sb, 16384, 16, 1), wg);
        const uint32_t lama = sb + OFF_LAM + wg * 1024 + w * 256 + (fresh_lane() & 28) * 4;
        mbar_wait_fast(bars + B_LAM, 0);
        lam[0] = lds_cf(lama); lam[1] = lds_cf(lama + 128);
        asm volatile("ld.shared.u32 %0, [%1];" : "=r"(ep) : "r"(bars + B_EPOCH) : "memory");
        asm volatile("setmaxnreg.inc.sync.aligned.u32 176;");
        cf L[2] = {lam[0], lam[1]};
#pragma unroll
        for (int i = 0; i < 4; i++) { L[0] = csq(L[0]); L[1] = csq(L[1]); }
        asm volatile("" : "+f"(L[0].x), "+f"(L[0].y), "+f"(L[1].x), "+f"(L[1].y)::"memory");
        wg_wait<0>();
        ring_release(rg, 8 * wg);
        pin(d);
        STAMPW(1, 11);
        {
            const int lane = fresh_lane(), g = lane >> 2, q = lane & 3, mi = lane >> 3, gl = lane & 7;
            cf f[2], fb2[2];
#pragma unroll
            for (int i = 0; i < 17; i++) {
#pragma unroll
                for (int h = 0; h < 2; h++) {
                    const int r = 4 * (i >> 1) + 2 * h + (i & 1), r2 = 32 + 4 * ((i - 1) >> 1) + 2 * h + ((i - 1) & 1);
                    if (i < 16) f[h] = i ? cfma(lam[h], f[h], {d[r], -d[64 + r]}) : cf{d[r], -d[64 + r]};
                    if (i > 0) fb2[h] = i > 1 ? cfma(lam[h], fb2[h], {d[r2], -d[64 + r2]}) : cf{d[r2], -d[64 + r2]};
                    if (i && (h || !(YS & 8))) YIELD_S1();
                }
            }
            const uint8_t* cbase = (const uint8_t*)g_carry + (tc * 16 + wg * 8 + cb) * 512 + w * 64;
            const uint8_t* cptr = padd(cbase, g * 8);
            const unsigned tag = ep & 15u;
#pragma unroll
            for (int h = 0; h < 2; h++) { f[h] = cfma(L[h], f[h], fb2[h]); L[h] = csq(L[h]); }
            cf s0[2], s1[2], s2[2];
#pragma unroll
            for (int h = 0; h < 2; h++) {
                s0[h] = {__shfl_sync(~0u, f[h].x, 0, 4), __shfl_sync(~0u, f[h].y, 0, 4)};
                s1[h] = {__shfl_sync(~0u, f[h].x, 1, 4), __shfl_sync(~0u, f[h].y, 1, 4)};
                s2[h] = {__shfl_sync(~0u, f[h].x, 2, 4), __shfl_sync(~0u, f[h].y, 2, 4)};
            }
#pragma unroll
            for (int h = 0; h < 2; h++) {
                s1[h] = cfma(L[h], s0[h], s1[h]);
                s2[h] = cfma(L[h], s1[h], s2[h]);
                f[h] = cfma(L[h], s2[h], f[h]);
                asm volatile("{.reg .pred p; .reg .b64 a; setp.eq.u32 p, %3, 3; mov.b64 a, {%1,%2}; @p st.relaxed.gpu.global.b64 [%0], a;}" ::"l"(cptr + h * 256),
                             "r"((__float_as_uint(f[h].x) & ~15u) | tag), "f"(f[h].y), "r"(q) : "memory");
            }
            STAMPX(2, 12);
            cf gam = lds_cf(lama + 8);
            cf st = csel(q & 2, csel(q & 1, s2[0], s1[0]), csel(q & 1, s0[0], {0.f, 0.f}));
            const cf st1 = csel(q & 2, csel(q & 1, s2[1], s1[1]), csel(q & 1, s0[1], {0.f, 0.f}));
            cptr = padd(cbase - 4 * 8192, (3 - mi) * 8192 + gl * 8);
            const int nprev = tc - 1 - mi;
            const uint8_t* hptr = padd(g_H + (size_t)(tc * 32 + wg * 16 + (cb & 6)) * 16384 + ((cb & 1) * 4 + w) * 1024, g * 64 + ((q ^ (g >> 1)) << 4));
            const uint32_t hm = 4 * (g & 1) + (q ^ (g >> 1)) == (cb & 1) * 4 + w ? ~1u : ~0u;
            float u[64];
            uint64_t fv[4] = {tag, tag, tag, tag};
            prescale<0>(u, d, gam);
            gather(fv, cptr, nprev);
#pragma unroll 1
            for (int h = 0;; h++) {
                const cf L2 = csq(L[0]), M = csq(L2);
                cf M4 = csq(csq(M));
                M4 = {__shfl_sync(~0u, M4.x, 4 * gl), __shfl_sync(~0u, M4.y, 4 * gl)};
                cf lq = cmul(gam, cmul(csel(q & 1, L[0], {1.f, 0.f}), csel(q & 2, L2, {1.f, 0.f})));
                st = cmul(gam, st);
                asm volatile("pmevent 1;" : "+f"(lq.x), "+f"(lq.y), "+f"(st.x), "+f"(st.y));
#pragma unroll 1
                for (unsigned n = 0; __any_sync(~0u, (((uint32_t)fv[0] ^ tag) | ((uint32_t)fv[1] ^ tag) | ((uint32_t)fv[2] ^ tag) | ((uint32_t)fv[3] ^ tag)) & 15u) && n < SPIN_LIMIT; n++) gather(fv, cptr, nprev);
                if (!h) STAMPX(53, 54);
                cf P = as_cf(fv[3]), pj[4];
#pragma unroll
                for (int a = 2; a >= 0; a--) P = cfma(M4, P, as_cf(fv[a]));
                cptr += 256;
                asm volatile("" : "+f"(P.x), "+f"(P.y)::"memory");
                gather(fv, cptr, h ? -1 : nprev);
#pragma unroll
                for (int j = 3; j >= 0; j--) pj[j] = {__shfl_sync(~0u, P.x, g + 8 * j), __shfl_sync(~0u, P.y, g + 8 * j)};
                st = cfma(lq, cfma(M, cfma(M, cfma(M, pj[3], pj[2]), pj[1]), pj[0]), st);
                if (!h) STAMPX(3, 13);
                uint32_t keep = sb >> 28;
                scan2(u, lam[0], st, hptr, hm, ep & ~hm, keep);
                warp_arrive(bars + B_HOWN + wg * 16 + h * 8 + keep);
                if (h) break;
                STAMPW(4, 14);
                if (wg == 1 && nu) bar_sync(9, 256);
                lds128f(lama + 128, lam[0].x, lam[0].y, gam.x, gam.y);
                st = st1;
                L[0] = L[1];
                hptr += 8 * 16384;
                prescale<1>(u, d, gam);
            }
            STAMPW(5, 15);
        }
        if (wg == 0) bar_sync(4, 128); else bar_sync(8, 128);
        if (wg == 0) {
            asm volatile("setmaxnreg.dec.sync.aligned.u32 160;");
            float y[128];
            rg = ring_at(sb, role * 66 + 32);
            STAMP(6);
            STAMP(7);
            const uint64_t dA = ring_desc(sb, 0, 512, 2), dB = ring_desc(sb, 16384, 16, 1);
            gemm2(y, rg, dA, dB, 0);
            asm volatile("setmaxnreg.inc.sync.aligned.u32 184;");
            const int lane = fresh_lane(), g = lane >> 2, q = lane & 3;
            const int pg = 2 * (g & 3) + (g >> 2);
            float* op = (float*)padd(p.out + (size_t)(tc * 128 + 64 * (w & 1) + 8 * (w >> 1)) * 2048 + 1024 + cb * 128, pg * 8192 + q * 16);
            const uint32_t xa = sb + OFF_F + (16 * (w & 1) + 8 * (w >> 1) + pg) * 128 + (((q >> 1) ^ pg) << 4) + (q & 1) * 8;
#define HALF0(k) wg_fence(); peek(k < 63 ? rg.full + SL(k + 1) * 8 : bars + B_XD, PH(k + 1)); half_step<0, k>(y, dA, dB); wg_commit(); peek_wait(k < 63 ? rg.full + SL(k + 1) * 8 : bars + B_XD, PH(k + 1), rg.n);
            HALF0(60) HALF0(61) HALF0(62) HALF0(63)
            const uint64_t dB2 = ring_desc(sb >> 1, 16384, 16, 1);
            uint32_t xa0[8], xa1[8], dd[16];
#pragma unroll
            for (int i = 0; i < 8; i++) asm volatile("ld.shared.v2.b32 {%0,%1}, [%2];" : "=r"(dd[2 * i]), "=r"(dd[2 * i + 1]) : "r"(sb + OFF_LAM + q * 8 + 32 * i) : "memory");
            load_x4<0, 0>(xa0, xa);
            wg_fence();
            half_step<64, 64 - SKEW>(y, dA, dB2);
            wg_commit();
            wg_wait<1>();
#pragma unroll
            for (int i = 0; i < 64; i++) asm volatile("" : "+f"(y[i])::"memory");
            STAMP(16);
#define MM(n) if (4 + (n) < 4 * SKEW) { wg_fence(); mma_h<64, 65 - SKEW + (n) / 4, (n) % 4>(y, dA, dB2); mma_h<64, 65 - SKEW + (n) / 4, (n) % 4 + 1>(y, dA, dB2); }
#define OUT4(R, U, X, n) out_piece<R, U>(y, dd, X[0], X[1], op); MM(n) out_piece<R, U + 1>(y, dd, X[2], X[3], op); MM(n + 2) \
                         out_piece<R, U + 2>(y, dd, X[4], X[5], op); MM(n + 4) out_piece<R, U + 3>(y, dd, X[6], X[7], op); MM(n + 6)
            load_x4<0, 4>(xa1, xa);
            OUT4(0, 0, xa0, 0)
            load_x4<1, 0>(xa0, xa);
            OUT4(0, 4, xa1, 8)
            wg_commit();
            load_x4<1, 4>(xa1, xa);
            OUT4(1, 0, xa0, 16)
            load_x4<2, 0>(xa0, xa);
            OUT4(1, 4, xa1, 16)
            STAMP(18);
            wg_wait<0>();
#pragma unroll
            for (int i = 64; i < 128; i++) asm volatile("" : "+f"(y[i])::"memory");
            STAMP(8);
            load_x4<2, 4>(xa1, xa);
            mbar_wait_fast(bars + B_XD + 8, 0);
            OUT4(2, 0, xa0, 16)
            load_x4<3, 0>(xa0, xa);
            OUT4(2, 4, xa1, 16)
            load_x4<3, 4>(xa1, xa);
            OUT4(3, 0, xa0, 16)
            OUT4(3, 4, xa1, 16)
            STAMP(9);
            return;
        }
        asm volatile("setmaxnreg.dec.sync.aligned.u32 152;");
        } else {
        if (nu) {
            cf T[8];
            ldtab_cf<2048>(T, TAB_T + t7 * 16);
            const uint32_t ep = get_epoch(bars);
            const int ka = pos_of(t7 >> 2);
            asm volatile("setp.eq.u32 p0, %0, 0;" ::"r"(__shfl_sync(~0u, t7, lane)));
            mbar_wait(bars + B_WSP, 0);
            mbar_wait(bars + B_FG, 0);
            uint32_t wd[4], wm[4], vo[32];
            const uint8_t* vp;
            int slot;
            const int kap0 = unit_of(role, 0, slot), al = 2 * kap0;
            const int kap1 = __shfl_sync(~0u, unit_of(role, 1, slot), 0);
            slot = __shfl_sync(~0u, slot, 0);
            cf be1 = twid(kap0 + 512 * q, 2048), be2 = csq(be1), be3 = cmul(be1, be2);
#pragma unroll
            for (int j = 0; j < 4; j++) {
                wd[j] = sb + OFF_WD + ((j + q) & 3) * WPITCH + (al & 15) + 2 * ka + 64 * q;
                wm[j] = sb + OFF_WM + (((role ? 3 : 4) - j - q) & 3) * WPITCH + (-al & 15) + 1024 - 2 * ka - 64 * q;
                wd[j] = __shfl_sync(~0u, wd[j], lane);
            }
#pragma unroll 1
            for (int u = 0; u < nu; u++) {
                const uint32_t buf = sb + OFF_P + u * 16384;
                float acc[64], za[32], zb[32], ya[32], yb[32], vv[64];
                const uint64_t dF = opaque(mkdesc(sb + OFF_F, 16, 1024, 1)), dB = opaque(mkdesc(buf, 4096, 512, 2));
                mbar_wait(bars + B_IN + u * 8, 0);
                if (!role) {
                    const uint32_t z = buf + w * 1024 + (fresh_lane() >> 2) * 128 + 64 + (fresh_lane() & 3) * 16;
#pragma unroll
                    for (int i = 0; i < 4; i++) sts128(z + i * 4096, 0, 0, 0, 0);
                    fence_async_sm();
                    bar_sync(3, 128);
                }
                STAMP3(22);
                wg_fence();
#pragma unroll
                for (int j = 0; j < 4; j++) mma128_ss<0, 0, 1>(acc, dF + j * 2, dB + j * 64, j);
                wg_commit();
                if (u) {
                    const uint32_t va = sb + OFF_P + (((uint32_t)(uintptr_t)vp - (uint32_t)(uintptr_t)g_X) >> 9 & 0x7c0) + ((uint32_t)(uintptr_t)vp & 31) + (fresh_lane() & 4) * 8;
                    bar_sync(3, 128);
#pragma unroll
                    for (int k = 0; k < 16; k++) sts64(va + ((k >> 1) & 1) * 8192 + (k >> 2) * 2048 + (k & 1) * 256, vo[2 * k], vo[2 * k + 1]);
                    fence_async_sm();
                    warp_arrive(bars + B_STG);
                    if (!role) { const uint32_t t = wm[0]; wm[0] = wm[1]; wm[1] = wm[2]; wm[2] = wm[3]; wm[3] = t; }
                }
                STAMP3(39);
                wg_wait<0>();
                pin(acc);
                STAMP3(30);
                uint32_t af[16], ag[16];
#pragma unroll
                for (int k = 0; k < 8; k++) {
                    uint32_t(&o)[16] = k < 4 ? af : ag;
                    const int c = k & 3;
#pragma unroll
                    for (int b = 0; b < 2; b++) {
                        const int i = 4 * (4 * ((k >> 2) * 2 + b) + c);
                        c2 x = mul2(c2{{acc[i], acc[i + 2]}, {acc[i + 1], acc[i + 3]}}, c2{T[2 * c], T[2 * c + 1]});
                        o[4 * c + b] = pk(x.a.x, x.a.y);
                        o[4 * c + 2 + b] = pk(x.b.x, x.b.y);
                    }
                    asm volatile("" : "+r"(o[4 * c]), "+r"(o[4 * c + 1]), "+r"(o[4 * c + 2]), "+r"(o[4 * c + 3])::"memory");
                    wg_fence();
                    mma64_rs<0>(k < 4 ? za : zb, o[4 * c], o[4 * c + 1], o[4 * c + 2], o[4 * c + 3], dF + c * 2, c);
                }
                wg_commit();
                STAMP3(31);
                mbar_wait(bars + B_WD, u & 1);
                uint32_t wr[16];
#pragma unroll
                for (int i = 0; i < 16; i++) wr[i] = lds16(wd[i >> 2] + 256 * ((i >> 1) & 1) + (i & 1) * 4 * WPITCH);
                wg_wait<0>();
                pin(za);
                pin(zb);
                pinu(af);
                pinu(ag);
                STAMP3(32);
#pragma unroll
                for (int jb = 0; jb < 4; jb++) {
                    const int i = 8 * jb;
                    c2 s0 = {{za[i], za[i + 4]}, {za[i + 1], za[i + 5]}}, s2 = {{za[i + 2], za[i + 6]}, {za[i + 3], za[i + 7]}};
                    c2 s1 = {{zb[i], zb[i + 4]}, {zb[i + 1], zb[i + 5]}}, s3 = {{zb[i + 2], zb[i + 6]}, {zb[i + 3], zb[i + 7]}};
                    c2 W[4];
                    auto wcvt = [&](int j) {
                        asm volatile("shl.b32 %0, %4, 16; shl.b32 %1, %5, 16; shl.b32 %2, %6, 16; shl.b32 %3, %7, 16;"
                                     : "=&f"(W[j].a.x), "=&f"(W[j].a.y), "=&f"(W[j].b.x), "=&f"(W[j].b.y) : "r"(wr[4 * j]), "r"(wr[4 * j + 1]), "r"(wr[4 * j + 2]), "r"(wr[4 * j + 3]));
                        if ((jb & 1) == 0)
                            asm volatile("@p0 ld.shared.v2.f32 {%0,%1}, [%2];" : "+f"(W[j].a.x), "+f"(W[j].a.y) : "r"(sb + OFF_WSP + u * 64 + jb * 16 + j * 8));
                        if (jb < 3) {
#pragma unroll
                            for (int k = 4 * j; k < 4 * j + 4; k++) {
                                const int e = (k >> 1) & 1, pl = (k & 1) * 4 * WPITCH;
                                wr[k] = jb == 0 ? lds16(wd[j] + 512 + 256 * e + pl) : lds16(wm[j] - 512 * (jb - 1) - 256 * e + pl);
                            }
                        }
                        if (jb >= 2) { W[j].a.y = -W[j].a.y; W[j].b.y = -W[j].b.y; }
                    };
                    wcvt(0);
                    s2 = mul2(s2, be1);
                    s1 = fma2(s1, be2, s0);
                    wcvt(1);
                    s3 = fma2(s3, be3, s2);
                    { const c2 x = twm2(s0, s1), y = twm2(s2, s3); s0 = s1; s2 = s3; s1 = x; s3 = y; }
                    wcvt(2);
                    bfly<0>(s0, s2); bfly_mi<0>(s1, s3);
                    wcvt(3);
                    s0 = mul2(s0, W[0]); s1 = mul2(s1, W[1]);
                    bfly_tw<0>(s0, s2, W[2], s1, s3, W[3]);
                    bfly<0>(s0, s1); bfly_mi<0>(s2, s3);
                    af[4 * jb] = pk(s0.a.x, s0.b.x); af[4 * jb + 1] = pk(s3.a.x, s3.b.x); af[4 * jb + 2] = pk(s0.a.y, s0.b.y); af[4 * jb + 3] = pk(s3.a.y, s3.b.y);
                    ag[4 * jb] = pk(s1.a.x, s1.b.x); ag[4 * jb + 1] = pk(s2.a.x, s2.b.x); ag[4 * jb + 2] = pk(s1.a.y, s1.b.y); ag[4 * jb + 3] = pk(s2.a.y, s2.b.y);
                }
                pinu(af);
                pinu(ag);
                warp_arrive(bars + B_WFREE);
                wg_fence();
#pragma unroll
                for (int j = 0; j < 4; j++) mma64_rs<1>(ya, af[4 * j], af[4 * j + 1], af[4 * j + 2], af[4 * j + 3], dF + j * 128, j);
                wg_commit();
#pragma unroll
                for (int j = 0; j < 4; j++) mma64_rs<1>(yb, ag[4 * j], ag[4 * j + 1], ag[4 * j + 2], ag[4 * j + 3], dF + j * 128, j);
                wg_commit();
                STAMP3(33);
                {
                    const uint32_t a0 = buf + (mi & 1) * 4096 + (16 * w + 8 * (mi >> 1) + gl) * 64 + ((gl >> 1) << 4);
#pragma unroll
                    for (int h = 0; h < 2; h++) {
                        if (h == 0) { wg_wait<1>(); pin(ya); pinu(af); STAMP3(34); } else { wg_wait<0>(); pin(yb); pinu(ag); }
                        const float(&yy)[32] = h ? yb : ya;
#pragma unroll
                        for (int c = 0; c < 4; c++) {
                            const int i = 8 * ((c + 2 * h) & 3), k = 8 * ((c + 2 * h + 1) & 3) + 2;
                            c2 x = {cmulc({yy[i], yy[i + 1]}, T[2 * c]), cmulc({yy[k], yy[k + 1]}, T[2 * c])};
                            fin<1>(x);
                            c2 y = {cmulc({yy[i + 4], yy[i + 5]}, T[2 * c + 1]), cmulc({yy[k + 4], yy[k + 5]}, T[2 * c + 1])};
                            fin<1>(y);
                            stsm4((a0 ^ (c << 4)) + h * 8192, pk(x.a.x, y.a.x), pk(x.b.x, y.b.x), pk(x.a.y, y.a.y), pk(x.b.y, y.b.y));
                        }
                    }
                }
                STAMP3(38);
                fence_async_sm();
                bar_sync(3, 128);
                wg_fence();
#pragma unroll
                for (int j = 0; j < 4; j++) mma128_ss<0, 1, 1>(vv, dF + j * 128, dB + j * 64, j);
                wg_commit();
                STAMP3(35);
                const int lane = fresh_lane(), g = lane >> 2, q = lane & 3;
                vp = padd(g_X + (4 << 20) + w * (8 * 32768) + (role ? u : 1) * 16384 + slot * 64,
                                         (g >> 1) * 32768 + (role ? g & 1 : u) * 32 + (((q ^ (slot >> 1)) & 1) << 4) + (q >> 1) * 8);
                const uint32_t tmask = (((g & 1) == ((slot >> 3) & 1) || !role) && q == ((slot >> 1) & 2)) ? ~1u : ~0u, tbit = (ep ^ (role + u ? 0 : g)) & ~tmask;
                be1 = twid(kap1 + 512 * q, 2048); be2 = csq(be1); be3 = cmul(be1, be2);
                asm volatile("pmevent 1;" : "+f"(be1.x), "+f"(be1.y), "+f"(be2.x), "+f"(be2.y), "+f"(be3.x), "+f"(be3.y), "+l"(vp)::"memory");
                wg_wait<0>();
                pin(vv);
                STAMP3(36);
#pragma unroll
                for (int k = 0; k < 16; k++) {
                    const int i = 8 * (k >> 1) + 2 * (k & 1);
                    vo[2 * k] = (pk(vv[i], vv[i + 1]) & tmask) | tbit;
                    vo[2 * k + 1] = pk(vv[i + 4], vv[i + 5]);
                }
                pinu(vo);
            }
            if (!role) mbar_wait(bars + B_IN + 16, 0);
            warp_arrive(bars + B_STG);
            const bool odd = fresh_lane() & 4;
            store_v<0, 4>(vo, vp, role || !odd);
            asm volatile("@p0 red.relaxed.gpu.global.add.u32 [%0], 1;" ::"l"(g_cnt + 32 + nu * 32) : "memory");
            store_v<4, 16>(vo, vp, role || odd);
            if (!spare) bar_arrive(9, 256);
        }
        if (spare) return;
        }
        {
            constexpr int Y = YP3;
            uint32_t sp[8];
            cf tw[8];
            ldtab<2, 2048>(sp, TAB_SP + fb * 4096 + t7 * 16);
            ldtab_cf<16>(tw, TAB_TW3 + fb * 2048 + (t7 >> 2) * 64);
            const uint64_t dF = opaque(mkdesc(sb + OFF_F, 16, 1024, 1)), dB = opaque(mkdesc(sb + OFF_P + hf * 8192, 1024, 256, 3));
            const uint8_t* op = padd(p.out + (1024 + fb) * 2048 + fcb * 32 + hf * 16, (t7 >> 2) * 32768 + (q >> 1) * 16 + (q & 1) * 32);
            float acc[64], out[64];
            mbar_wait(bars + B_IN + 24, 0);
            mbar_wait(bars + B_FG, 1);
            STAMP(25);
            pinu(sp);
            wg_fence();
#pragma unroll
            for (int j = 0; j < 4; j++) {
                const uint64_t db = dB + (j >> 1) * 1024 + (j & 1) * 32;
                mma112_ss(acc, dF + j * 2, db + 64, j);
                if (j & 1) mma16_rs(acc, 0u, sp[2 * j], 0u, sp[2 * j + 1], db, 1);
                else mma16_rs(acc, sp[2 * j], 0u, sp[2 * j + 1], 0u, db, j);
            }
            wg_commit();
            wg_wait<0>();
            pin(acc);
            pinu(sp);
            warp_arrive(bars + B_P3M);
            if (!hf) bar_sync(5, 256);
#pragma unroll
            for (int cl = 0; cl < 2; cl++) {
                c2 z[8];
#pragma unroll
                for (int n = 0; n < 8; n++) {
                    const int i = 4 * (2 * n + cl);
                    z[n] = {{acc[i], acc[i + 2]}, {acc[i + 1], acc[i + 3]}};
                }
                z[0] = {{z[0].a.x + z[0].a.y, z[0].a.x - z[0].a.y}, {z[0].b.x + z[0].b.y, z[0].b.x - z[0].b.y}};
                z[4] = mul2(z[4], tw[4]);
                fin<Y>(z[0], z[4]);
#pragma unroll
                for (int n = 1; n < 4; n++) {
                    const cf iw = n == 1 ? cf{0.38268343236508977f, 0.92387953251128674f}
                                         : (n == 2 ? cf{0.70710678118654752f, 0.70710678118654752f} : cf{0.92387953251128674f, 0.38268343236508977f});
                    c2 y = mul2(z[n], tw[n]);
                    fin<Y>(y);
                    const cf t = {tw[8 - n].x, -tw[8 - n].y};
                    c2 E = fma2(c2{{z[8 - n].a.x, -z[8 - n].a.y}, {z[8 - n].b.x, -z[8 - n].b.y}}, t, y);
                    fin<Y>(E);
                    z[n] = fma2(twm2(y, E), iw, E);
                    fin<Y>(z[n]);
                    z[8 - n] = {{fmaf(2.f, E.a.x, -z[n].a.x), fmaf(-2.f, E.a.y, z[n].a.y)}, {fmaf(2.f, E.b.x, -z[n].b.x), fmaf(-2.f, E.b.y, z[n].b.y)}};
                }
                dft8<false, Y>(z, tw);
#pragma unroll
                for (int m = 0; m < 8; m++) {
                    out[8 * m + 2 * cl] = z[m].a.x; out[8 * m + 2 * cl + 1] = z[m].b.x;
                    out[8 * m + 4 + 2 * cl] = z[m].a.y; out[8 * m + 5 + 2 * cl] = z[m].b.y;
                }
            }
            pin(out);
            if (hf) bar_arrive(5, 256);
            if (hf) STAMP(26);
#pragma unroll
            for (int m = 0; m < 16; m++) {
                asm volatile("st.global.v4.f32 [%0], {%1,%2,%3,%4};" ::"l"(op + (m - 8) * (1 << 20)), "f"(out[4 * m]), "f"(out[4 * m + 1]), "f"(out[4 * m + 2]), "f"(out[4 * m + 3]) : "memory");
                if (PACE_O && m < 15 && m % PACE_ON == PACE_ON - 1)
                    asm volatile("{.reg .pred p; mbarrier.test_wait.parity.shared::cta.b64 p, [%0], 0; @!p nanosleep.u32 %1;}" ::"r"(bars + B_DONE), "n"(PACE_O) : "memory");
            }
            STAMP(27);
        }
    }
}

typedef CUresult (*EncodeFn)(CUtensorMap*, CUtensorMapDataType, cuuint32_t, void*, const cuuint64_t*, const cuuint64_t*, const cuuint32_t*,
                             const cuuint32_t*, CUtensorMapInterleave, CUtensorMapSwizzle, CUtensorMapL2promotion, CUtensorMapFloatOOBfill);

static CUtensorMap make_map(EncodeFn enc, const void* ptr, int rank, const cuuint64_t* dims, const cuuint64_t* strides, const cuuint32_t* box,
                            CUtensorMapSwizzle swz, CUtensorMapL2promotion promo, CUtensorMapDataType dt = CU_TENSOR_MAP_DATA_TYPE_BFLOAT16) {
    CUtensorMap m;
    const cuuint32_t es[5] = {1, 1, 1, 1, 1};
    enc(&m, dt, rank, const_cast<void*>(ptr), dims, strides, box, es, CU_TENSOR_MAP_INTERLEAVE_NONE, swz, promo,
        CU_TENSOR_MAP_FLOAT_OOB_FILL_NONE);
    return m;
}

extern "C" void kernel_launch(void* const* d_in, const int* in_sizes, int n_in, void* d_out, int out_size) {
    void* fn = nullptr;
    cudaDriverEntryPointQueryResult qr;
    cudaGetDriverEntryPoint("cuTensorMapEncodeTiled", &fn, cudaEnableDefault, &qr);
    EncodeFn enc = (EncodeFn)fn;
    void* pX;
    cudaGetSymbolAddress(&pX, g_X);
    const CUtensorMapL2promotion P256 = CU_TENSOR_MAP_L2_PROMOTION_L2_256B, P0 = CU_TENSOR_MAP_L2_PROMOTION_NONE;

    const cuuint64_t dX[5] = {1024, 2, 4, 16, 16}, sX[4] = {2048, 32 * 2048, 2 * 2048, 128 * 2048};
    const cuuint32_t bX[5] = {64, 2, 4, 16, 1};
    CUtensorMap tmX = make_map(enc, d_in[3], 5, dX, sX, bX, CU_TENSOR_MAP_SWIZZLE_128B, P256);
    const cuuint64_t dXd[4] = {64, 2048, 2, 16}, sXd[3] = {2048, 64 * 2048, 128};
    const cuuint32_t bXd[4] = {64, 16, 2, 2};
    CUtensorMap tmXd = make_map(enc, d_in[3], 4, dXd, sXd, bXd, CU_TENSOR_MAP_SWIZZLE_128B, P256);
    const cuuint64_t dB[4] = {1024, 8, 4, 32}, sB[3] = {2048, 256 * 2048, 8 * 2048};
    const cuuint32_t bB4[4] = {64, 8, 2, 4};
    CUtensorMap tmBre = make_map(enc, d_in[6], 4, dB, sB, bB4, CU_TENSOR_MAP_SWIZZLE_128B, P256);
    CUtensorMap tmBim = make_map(enc, d_in[7], 4, dB, sB, bB4, CU_TENSOR_MAP_SWIZZLE_128B, P256);
    const cuuint64_t dC[5] = {1024, 2, 4, 2, 64}, sC[4] = {2048, 4 * 2048, 2 * 2048, 16 * 2048};
    const cuuint32_t bC[5] = {64, 2, 4, 2, 4};
    CUtensorMap tmCre = make_map(enc, d_in[8], 5, dC, sC, bC, CU_TENSOR_MAP_SWIZZLE_128B, P256);
    CUtensorMap tmCim = make_map(enc, d_in[9], 5, dC, sC, bC, CU_TENSOR_MAP_SWIZZLE_128B, P256);

    const cuuint64_t dU[2] = {8192, 256}, sU[1] = {16384};
    const cuuint32_t bU[2] = {64, 64};
    CUtensorMap tmUst = make_map(enc, pX, 2, dU, sU, bU, CU_TENSOR_MAP_SWIZZLE_128B, P0);
    const cuuint64_t dV[2] = {16384, 128}, sV[1] = {32768};
    const cuuint32_t bV[2] = {32, 128};
    CUtensorMap tmVst = make_map(enc, (uint8_t*)pX + (4 << 20), 2, dV, sV, bV, CU_TENSOR_MAP_SWIZZLE_NONE, P0);
    const cuuint64_t dF[2] = {512 * 1026 / 8, 4}, sF[1] = {512 * 1026};
    const cuuint32_t bF[2] = {WPITCH / 8, 4};
    CUtensorMap tmWr = make_map(enc, d_in[1], 2, dF, sF, bF, CU_TENSOR_MAP_SWIZZLE_NONE, P0, CU_TENSOR_MAP_DATA_TYPE_UINT64);
    CUtensorMap tmWi = make_map(enc, d_in[2], 2, dF, sF, bF, CU_TENSOR_MAP_SWIZZLE_NONE, P0, CU_TENSOR_MAP_DATA_TYPE_UINT64);

    const cuuint64_t dA[3] = {1024, 64, 32}, sA[2] = {32 * 2048, 2048};
    const cuuint32_t bA[3] = {32, 64, 1};
    CUtensorMap tmXa = make_map(enc, d_in[0], 3, dA, sA, bA, CU_TENSOR_MAP_SWIZZLE_64B, CU_TENSOR_MAP_L2_PROMOTION_L2_128B);

    Params p;
    p.wr = (const __nv_bfloat16*)d_in[1];
    p.wi = (const __nv_bfloat16*)d_in[2];
    p.lre = (const __nv_bfloat16*)d_in[4];
    p.lim = (const __nv_bfloat16*)d_in[5];
    p.ldt = (const __nv_bfloat16*)d_in[10];
    p.dsk = (const __nv_bfloat16*)d_in[11];
    p.out = (float*)d_out;
    int dev = 0, sms = 0;
    cudaGetDevice(&dev);
    cudaDeviceGetAttribute(&sms, cudaDevAttrMultiProcessorCount, dev);
    auto kernel = sms == 132 ? fused_kernel<true> : fused_kernel<false>;
    cudaFuncSetAttribute(kernel, cudaFuncAttributeMaxDynamicSharedMemorySize, SMEM_BYTES);
    kernel<<<132, 512, SMEM_BYTES>>>(tmX, tmBre, tmBim, tmCre, tmCim, tmXd, tmUst, tmVst, tmWr, tmWi, tmXa, p);
}
```

```cpp
#include <cuda_runtime.h>
#include <cuda.h>
#include <cuda_bf16.h>
#include <stdint.h>

#define NST 5
#define WPITCH 1056
#define OFF_P (NST * 32768)
#define OFF_F (OFF_P + 32768)
#define OFF_WD (OFF_F + 8192)
#define OFF_WM (OFF_WD + 8 * WPITCH)
#define OFF_BAR (OFF_F + 32768)
#define OFF_LAM (OFF_BAR + 432)
#define OFF_WSP (OFF_LAM + 2048)
#define OFF_PROF (OFF_WSP + 128)
#define SMEM_BYTES OFF_PROF
#define B_FULL 0
#define B_HL 40
#define B_EP 120
#define B_HR 128
#define B_XD 144
#define B_FG 160
#define B_WSP 168
#define B_WD 176
#define B_DONE 184
#define B_LD 192
#define B_RAW 200
#define B_LAM 208
#define B_IN 216
#define B_XIN 248
#define B_EMPTY 256
#define B_STG 320
#define B_WFREE 328
#define B_HOWN 336
#define B_STGU 368
#define B_P3M 384
#define B_EPOCH 416

#define XA_PACE 200
#define PACE_O 200
#define PACE_ON 2
#define TAB_T0 500
#define LAM_T0 1000
#define WT0 200
#define WN 1
#define XA_N0 2
#define PACE_X 200
#define SKEW 4
#define SPIN_LIMIT (1u << 15)

__device__ __align__(1024) uint8_t g_X[8 << 20];
__device__ __align__(1024) uint8_t g_H[8 << 20];
__device__ __align__(1024) uint4 g_carry[16 * 512];
__device__ __align__(128) unsigned g_cnt[128];
__device__ __align__(128) unsigned g_epoch[132 * 8];

#define STAMP(i) do { } while (0)
#define STAMPO(i, o) do { } while (0)
#define STAMPW(a, b) do { } while (0)
#define STAMPX(a, b) do { } while (0)
#define STAMP5(i) do { } while (0)
#define STAMP3(i) do { } while (0)

#define TAB_FG 0
#define TAB_G 8192
#define TAB_F1 40960
#define TAB_T 49152
#define TAB_SP 57344
#define TAB_TW1 73728
#define TAB_TW3 75776
#define TAB_PC 83968
__device__ __align__(1024) const uint32_t g_tab[21248] = {
0x80003d80,0x80003d80,0x80003d80,0x80003d80,0x80003d80,0x80003d80,0x80003d80,0x80003d80,0x80003d80,0x80003d80,0x80003d80,0x80003d80,0x80003d80,0x80003d80,0x80003d80,0x80003d80,
0x80003d80,0x80003d80,0x80003d80,0x80003d80,0x80003d80,0x80003d80,0x80003d80,0x80003d80,0x80003d80,0x80003d80,0x80003d80,0x80003d80,0x80003d80,0x80003d80,0x80003d80,0x80003d80,
0x3d353d35,0x3d35bd35,0xbd35bd35,0xbd353d35,0x80003d80,0x3d800000,0x8000bd80,0xbd800000,0x3d353d35,0x3d35bd35,0xbd35bd35,0xbd353d35,0x80003d80,0x3d800000,0x8000bd80,0xbd800000,
0x3d353d35,0x3d35bd35,0xbd35bd35,0xbd353d35,0x80003d80,0x3d800000,0x8000bd80,0xbd800000,0x3d353d35,0x3d35bd35,0xbd35bd35,0xbd353d35,0x80003d80,0x3d800000,0x8000bd80,0xbd800000,
0x3d800000,0x3d6dbcc4,0x3d35bd35,0x3cc4bd6d,0x3d7bbc48,0x3d55bd0e,0x3d0ebd55,0x3c48bd7b,0x80003d80,0x3cc43d6d,0x3d353d35,0x3d6d3cc4,0x3c483d7b,0x3d0e3d55,0x3d553d0e,0x3d7b3c48,
0xbd800000,0xbd6d3cc4,0xbd353d35,0xbcc43d6d,0xbd7b3c48,0xbd553d0e,0xbd0e3d55,0xbc483d7b,0x8000bd80,0xbcc4bd6d,0xbd35bd35,0xbd6dbcc4,0xbc48bd7b,0xbd0ebd55,0xbd55bd0e,0xbd7bbc48,
0x3d0ebd55,0xbd7bbc48,0x3c483d7b,0x3d55bd0e,0x3d800000,0xbcc4bd6d,0xbd353d35,0x3d6d3cc4,0x3d553d0e,0x3c48bd7b,0xbd7b3c48,0x3d0e3d55,0x80003d80,0x3d6dbcc4,0xbd35bd35,0xbcc43d6d,
0xbd0e3d55,0x3d7b3c48,0xbc48bd7b,0xbd553d0e,0xbd800000,0x3cc43d6d,0x3d35bd35,0xbd6dbcc4,0xbd55bd0e,0xbc483d7b,0x3d7bbc48,0xbd0ebd55,0x8000bd80,0xbd6d3cc4,0x3d353d35,0x3cc4bd6d,
0x80003d80,0x3d353d35,0x3d800000,0x3d35bd35,0x3cc43d6d,0x3d6d3cc4,0x3d6dbcc4,0x3cc4bd6d,0x8000bd80,0xbd35bd35,0xbd800000,0xbd353d35,0xbcc4bd6d,0xbd6dbcc4,0xbd6d3cc4,0xbcc43d6d,
0x80003d80,0x3d353d35,0x3d800000,0x3d35bd35,0x3cc43d6d,0x3d6d3cc4,0x3d6dbcc4,0x3cc4bd6d,0x8000bd80,0xbd35bd35,0xbd800000,0xbd353d35,0xbcc4bd6d,0xbd6dbcc4,0xbd6d3cc4,0xbcc43d6d,
0x3d6d3cc4,0xbcc4bd6d,0xbcc43d6d,0x3d6dbcc4,0x80003d80,0x3d35bd35,0xbd800000,0x3d353d35,0xbd6dbcc4,0x3cc43d6d,0x3cc4bd6d,0xbd6d3cc4,0x8000bd80,0xbd353d35,0x3d800000,0xbd35bd35,
0x3d6d3cc4,0xbcc4bd6d,0xbcc43d6d,0x3d6dbcc4,0x80003d80,0x3d35bd35,0xbd800000,0x3d353d35,0xbd6dbcc4,0x3cc43d6d,0x3cc4bd6d,0xbd6d3cc4,0x8000bd80,0xbd353d35,0x3d800000,0xbd35bd35,
0x3d800000,0x3cc4bd6d,0xbd35bd35,0xbd6d3cc4,0x3d55bd0e,0xbc48bd7b,0xbd7bbc48,0xbd0e3d55,0x8000bd80,0xbd6dbcc4,0xbd353d35,0x3cc43d6d,0xbd0ebd55,0xbd7b3c48,0xbc483d7b,0x3d553d0e,
0xbd800000,0xbcc43d6d,0x3d353d35,0x3d6dbcc4,0xbd553d0e,0x3c483d7b,0x3d7b3c48,0x3d0ebd55,0x80003d80,0x3d6d3cc4,0x3d35bd35,0xbcc4bd6d,0x3d0e3d55,0x3d7bbc48,0x3c48bd7b,0xbd55bd0e,
0x3c48bd7b,0xbd0e3d55,0x3d55bd0e,0xbd7b3c48,0x3d800000,0xbd6dbcc4,0x3d353d35,0xbcc4bd6d,0xbd7bbc48,0x3d553d0e,0xbd0ebd55,0x3c483d7b,0x8000bd80,0xbcc43d6d,0x3d35bd35,0xbd6d3cc4,
0xbc483d7b,0x3d0ebd55,0xbd553d0e,0x3d7bbc48,0xbd800000,0x3d6d3cc4,0xbd35bd35,0x3cc43d6d,0x3d7b3c48,0xbd55bd0e,0x3d0e3d55,0xbc48bd7b,0x80003d80,0x3cc4bd6d,0xbd353d35,0x3d6dbcc4,
0x3d800000,0x3d800000,0x3d800000,0x3d800000,0x3d800000,0x3d800000,0x3d800000,0x3d800000,0x3d800000,0x3d800000,0x3d800000,0x3d800000,0x3d800000,0x3d800000,0x3d800000,0x3d800000,
0x3d800000,0x3d800000,0x3d800000,0x3d800000,0x3d800000,0x3d800000,0x3d800000,0x3d800000,0x3d800000,0x3d800000,0x3d800000,0x3d800000,0x3d800000,0x3d800000,0x3d800000,0x3d800000,
0x3d35bd35,0xbd35bd35,0xbd353d35,0x3d353d35,0x3d800000,0xbd80,0xbd800000,0x3d80,0x3d35bd35,0xbd35bd35,0xbd353d35,0x3d353d35,0x3d800000,0xbd80,0xbd800000,0x3d80,
0x3d35bd35,0xbd35bd35,0xbd353d35,0x3d353d35,0x3d800000,0xbd80,0xbd800000,0x3d80,0x3d35bd35,0xbd35bd35,0xbd353d35,0x3d353d35,0x3d800000,0xbd80,0xbd800000,0x3d80,
0xbd80,0xbcc4bd6d,0xbd35bd35,0xbd6dbcc4,0xbc48bd7b,0xbd0ebd55,0xbd55bd0e,0xbd7bbc48,0x3d800000,0x3d6dbcc4,0x3d35bd35,0x3cc4bd6d,0x3d7bbc48,0x3d55bd0e,0x3d0ebd55,0x3c48bd7b,
0x3d80,0x3cc43d6d,0x3d353d35,0x3d6d3cc4,0x3c483d7b,0x3d0e3d55,0x3d553d0e,0x3d7b3c48,0xbd800000,0xbd6d3cc4,0xbd353d35,0xbcc43d6d,0xbd7b3c48,0xbd553d0e,0xbd0e3d55,0xbc483d7b,
0xbd55bd0e,0xbc483d7b,0x3d7bbc48,0xbd0ebd55,0xbd80,0xbd6d3cc4,0x3d353d35,0x3cc4bd6d,0x3d0ebd55,0xbd7bbc48,0x3c483d7b,0x3d55bd0e,0x3d800000,0xbcc4bd6d,0xbd353d35,0x3d6d3cc4,
0x3d553d0e,0x3c48bd7b,0xbd7b3c48,0x3d0e3d55,0x3d80,0x3d6dbcc4,0xbd35bd35,0xbcc43d6d,0xbd0e3d55,0x3d7b3c48,0xbc48bd7b,0xbd553d0e,0xbd800000,0x3cc43d6d,0x3d35bd35,0xbd6dbcc4,
0x3d800000,0x3d35bd35,0xbd80,0xbd35bd35,0x3d6dbcc4,0x3cc4bd6d,0xbcc4bd6d,0xbd6dbcc4,0xbd800000,0xbd353d35,0x3d80,0x3d353d35,0xbd6d3cc4,0xbcc43d6d,0x3cc43d6d,0x3d6d3cc4,
0x3d800000,0x3d35bd35,0xbd80,0xbd35bd35,0x3d6dbcc4,0x3cc4bd6d,0xbcc4bd6d,0xbd6dbcc4,0xbd800000,0xbd353d35,0x3d80,0x3d353d35,0xbd6d3cc4,0xbcc43d6d,0x3cc43d6d,0x3d6d3cc4,
0x3cc4bd6d,0xbd6d3cc4,0x3d6d3cc4,0xbcc4bd6d,0x3d800000,0xbd35bd35,0x3d80,0x3d35bd35,0xbcc43d6d,0x3d6dbcc4,0xbd6dbcc4,0x3cc43d6d,0xbd800000,0x3d353d35,0xbd80,0xbd353d35,
0x3cc4bd6d,0xbd6d3cc4,0x3d6d3cc4,0xbcc4bd6d,0x3d800000,0xbd35bd35,0x3d80,0x3d35bd35,0xbcc43d6d,0x3d6dbcc4,0xbd6dbcc4,0x3cc43d6d,0xbd800000,0x3d353d35,0xbd80,0xbd353d35,
0xbd80,0xbd6dbcc4,0xbd353d35,0x3cc43d6d,0xbd0ebd55,0xbd7b3c48,0xbc483d7b,0x3d553d0e,0xbd800000,0xbcc43d6d,0x3d353d35,0x3d6dbcc4,0xbd553d0e,0x3c483d7b,0x3d7b3c48,0x3d0ebd55,
0x3d80,0x3d6d3cc4,0x3d35bd35,0xbcc4bd6d,0x3d0e3d55,0x3d7bbc48,0x3c48bd7b,0xbd55bd0e,0x3d800000,0x3cc4bd6d,0xbd35bd35,0xbd6d3cc4,0x3d55bd0e,0xbc48bd7b,0xbd7bbc48,0xbd0e3d55,
0xbd7bbc48,0x3d553d0e,0xbd0ebd55,0x3c483d7b,0xbd80,0xbcc43d6d,0x3d35bd35,0xbd6d3cc4,0xbc483d7b,0x3d0ebd55,0xbd553d0e,0x3d7bbc48,0xbd800000,0x3d6d3cc4,0xbd35bd35,0x3cc43d6d,
0x3d7b3c48,0xbd55bd0e,0x3d0e3d55,0xbc48bd7b,0x3d80,0x3cc4bd6d,0xbd353d35,0x3d6dbcc4,0x3c48bd7b,0xbd0e3d55,0x3d55bd0e,0xbd7b3c48,0x3d800000,0xbd6dbcc4,0x3d353d35,0xbcc4bd6d,
0x80003d80,0x8000bd80,0x80003d80,0x8000bd80,0x3d800000,0xbd800000,0x3d800000,0xbd800000,0x80003d80,0x8000bd80,0x80003d80,0x8000bd80,0x3d800000,0xbd800000,0x3d800000,0xbd800000,
0x80003d80,0x8000bd80,0x80003d80,0x8000bd80,0x3d800000,0xbd800000,0x3d800000,0xbd800000,0x80003d80,0x8000bd80,0x80003d80,0x8000bd80,0x3d800000,0xbd800000,0x3d800000,0xbd800000,
0x3d35bd35,0x3d353d35,0xbd353d35,0xbd35bd35,0x80003d80,0xbd800000,0x8000bd80,0x3d800000,0x3d35bd35,0x3d353d35,0xbd353d35,0xbd35bd35,0x80003d80,0xbd800000,0x8000bd80,0x3d800000,
0x3d35bd35,0x3d353d35,0xbd353d35,0xbd35bd35,0x80003d80,0xbd800000,0x8000bd80,0x3d800000,0x3d35bd35,0x3d353d35,0xbd353d35,0xbd35bd35,0x80003d80,0xbd800000,0x8000bd80,0x3d800000,
0x3d800000,0xbd6d3cc4,0x3d35bd35,0xbcc43d6d,0xbc48bd7b,0x3d0e3d55,0xbd55bd0e,0x3d7b3c48,0x80003d80,0xbcc4bd6d,0x3d353d35,0xbd6dbcc4,0x3d7bbc48,0xbd553d0e,0x3d0ebd55,0xbc483d7b,
0xbd800000,0x3d6dbcc4,0xbd353d35,0x3cc4bd6d,0x3c483d7b,0xbd0ebd55,0x3d553d0e,0xbd7bbc48,0x8000bd80,0x3cc43d6d,0xbd35bd35,0x3d6d3cc4,0xbd7b3c48,0x3d55bd0e,0xbd0e3d55,0x3c48bd7b,
0xbd55bd0e,0x3c48bd7b,0x3d7bbc48,0x3d0e3d55,0x3d800000,0x3cc43d6d,0xbd353d35,0xbd6dbcc4,0x3d0ebd55,0x3d7b3c48,0x3c483d7b,0xbd553d0e,0x80003d80,0xbd6d3cc4,0xbd35bd35,0x3cc4bd6d,
0x3d553d0e,0xbc483d7b,0xbd7b3c48,0xbd0ebd55,0xbd800000,0xbcc4bd6d,0x3d35bd35,0x3d6d3cc4,0xbd0e3d55,0xbd7bbc48,0xbc48bd7b,0x3d55bd0e,0x8000bd80,0x3d6dbcc4,0x3d353d35,0xbcc43d6d,
0x80003d80,0xbd35bd35,0x3d800000,0xbd353d35,0x3d6dbcc4,0xbcc43d6d,0xbcc4bd6d,0x3d6d3cc4,0x8000bd80,0x3d353d35,0xbd800000,0x3d35bd35,0xbd6d3cc4,0x3cc4bd6d,0x3cc43d6d,0xbd6dbcc4,
0x80003d80,0xbd35bd35,0x3d800000,0xbd353d35,0x3d6dbcc4,0xbcc43d6d,0xbcc4bd6d,0x3d6d3cc4,0x8000bd80,0x3d353d35,0xbd800000,0x3d35bd35,0xbd6d3cc4,0x3cc4bd6d,0x3cc43d6d,0xbd6dbcc4,
0x3cc4bd6d,0x3d6dbcc4,0x3d6d3cc4,0x3cc43d6d,0x80003d80,0xbd353d35,0xbd800000,0xbd35bd35,0xbcc43d6d,0xbd6d3cc4,0xbd6dbcc4,0xbcc4bd6d,0x8000bd80,0x3d35bd35,0x3d800000,0x3d353d35,
0x3cc4bd6d,0x3d6dbcc4,0x3d6d3cc4,0x3cc43d6d,0x80003d80,0xbd353d35,0xbd800000,0xbd35bd35,0xbcc43d6d,0xbd6d3cc4,0xbd6dbcc4,0xbcc4bd6d,0x8000bd80,0x3d35bd35,0x3d800000,0x3d353d35,
0x3d800000,0xbcc43d6d,0xbd35bd35,0x3d6dbcc4,0xbd0ebd55,0x3d7bbc48,0xbc483d7b,0xbd55bd0e,0x8000bd80,0x3d6d3cc4,0xbd353d35,0xbcc4bd6d,0xbd553d0e,0xbc48bd7b,0x3d7b3c48,0xbd0e3d55,
0xbd800000,0x3cc4bd6d,0x3d353d35,0xbd6d3cc4,0x3d0e3d55,0xbd7b3c48,0x3c48bd7b,0x3d553d0e,0x80003d80,0xbd6dbcc4,0x3d35bd35,0x3cc43d6d,0x3d55bd0e,0x3c483d7b,0xbd7bbc48,0x3d0ebd55,
0xbd7bbc48,0xbd55bd0e,0xbd0ebd55,0xbc48bd7b,0x3d800000,0x3d6d3cc4,0x3d353d35,0x3cc43d6d,0xbc483d7b,0xbd0e3d55,0xbd553d0e,0xbd7b3c48,0x8000bd80,0x3cc4bd6d,0x3d35bd35,0x3d6dbcc4,
0x3d7b3c48,0x3d553d0e,0x3d0e3d55,0x3c483d7b,0xbd800000,0xbd6dbcc4,0xbd35bd35,0xbcc4bd6d,0x3c48bd7b,0x3d0ebd55,0x3d55bd0e,0x3d7bbc48,0x80003d80,0xbcc43d6d,0xbd353d35,0xbd6d3cc4,
0x3d800000,0xbd800000,0x3d800000,0xbd800000,0xbd80,0x3d80,0xbd80,0x3d80,0x3d800000,0xbd800000,0x3d800000,0xbd800000,0xbd80,0x3d80,0xbd80,0x3d80,
0x3d800000,0xbd800000,0x3d800000,0xbd800000,0xbd80,0x3d80,0xbd80,0x3d80,0x3d800000,0xbd800000,0x3d800000,0xbd800000,0xbd80,0x3d80,0xbd80,0x3d80,
0xbd35bd35,0x3d35bd35,0x3d353d35,0xbd353d35,0x3d800000,0x3d80,0xbd800000,0xbd80,0xbd35bd35,0x3d35bd35,0x3d353d35,0xbd353d35,0x3d800000,0x3d80,0xbd800000,0xbd80,
0xbd35bd35,0x3d35bd35,0x3d353d35,0xbd353d35,0x3d800000,0x3d80,0xbd800000,0xbd80,0xbd35bd35,0x3d35bd35,0x3d353d35,0xbd353d35,0x3d800000,0x3d80,0xbd800000,0xbd80,
0xbd80,0x3cc43d6d,0xbd35bd35,0x3d6d3cc4,0xbd7b3c48,0x3d55bd0e,0xbd0e3d55,0x3c48bd7b,0x3d800000,0xbd6d3cc4,0x3d35bd35,0xbcc43d6d,0xbc48bd7b,0x3d0e3d55,0xbd55bd0e,0x3d7b3c48,
0x3d80,0xbcc4bd6d,0x3d353d35,0xbd6dbcc4,0x3d7bbc48,0xbd553d0e,0x3d0ebd55,0xbc483d7b,0xbd800000,0x3d6dbcc4,0xbd353d35,0x3cc4bd6d,0x3c483d7b,0xbd0ebd55,0x3d553d0e,0xbd7bbc48,
0xbd0e3d55,0xbd7bbc48,0xbc48bd7b,0x3d55bd0e,0xbd80,0x3d6dbcc4,0x3d353d35,0xbcc43d6d,0xbd55bd0e,0x3c48bd7b,0x3d7bbc48,0x3d0e3d55,0x3d800000,0x3cc43d6d,0xbd353d35,0xbd6dbcc4,
0x3d0ebd55,0x3d7b3c48,0x3c483d7b,0xbd553d0e,0x3d80,0xbd6d3cc4,0xbd35bd35,0x3cc4bd6d,0x3d553d0e,0xbc483d7b,0xbd7b3c48,0xbd0ebd55,0xbd800000,0xbcc4bd6d,0x3d35bd35,0x3d6d3cc4,
0x3d800000,0xbd353d35,0xbd80,0x3d353d35,0xbcc4bd6d,0x3d6d3cc4,0xbd6d3cc4,0x3cc4bd6d,0xbd800000,0x3d35bd35,0x3d80,0xbd35bd35,0x3cc43d6d,0xbd6dbcc4,0x3d6dbcc4,0xbcc43d6d,
0x3d800000,0xbd353d35,0xbd80,0x3d353d35,0xbcc4bd6d,0x3d6d3cc4,0xbd6d3cc4,0x3cc4bd6d,0xbd800000,0x3d35bd35,0x3d80,0xbd35bd35,0x3cc43d6d,0xbd6dbcc4,0x3d6dbcc4,0xbcc43d6d,
0xbd6dbcc4,0xbcc4bd6d,0x3cc4bd6d,0x3d6dbcc4,0x3d800000,0x3d353d35,0x3d80,0xbd353d35,0x3d6d3cc4,0x3cc43d6d,0xbcc43d6d,0xbd6d3cc4,0xbd800000,0xbd35bd35,0xbd80,0x3d35bd35,
0xbd6dbcc4,0xbcc4bd6d,0x3cc4bd6d,0x3d6dbcc4,0x3d800000,0x3d353d35,0x3d80,0xbd353d35,0x3d6d3cc4,0x3cc43d6d,0xbcc43d6d,0xbd6d3cc4,0xbd800000,0xbd35bd35,0xbd80,0x3d35bd35,
0xbd80,0x3d6d3cc4,0xbd353d35,0xbcc4bd6d,0xbd553d0e,0xbc48bd7b,0x3d7b3c48,0xbd0e3d55,0xbd800000,0x3cc4bd6d,0x3d353d35,0xbd6d3cc4,0x3d0e3d55,0xbd7b3c48,0x3c48bd7b,0x3d553d0e,
0x3d80,0xbd6dbcc4,0x3d35bd35,0x3cc43d6d,0x3d55bd0e,0x3c483d7b,0xbd7bbc48,0x3d0ebd55,0x3d800000,0xbcc43d6d,0xbd35bd35,0x3d6dbcc4,0xbd0ebd55,0x3d7bbc48,0xbc483d7b,0xbd55bd0e,
0xbc483d7b,0xbd0e3d55,0xbd553d0e,0xbd7b3c48,0xbd80,0x3cc4bd6d,0x3d35bd35,0x3d6dbcc4,0x3d7b3c48,0x3d553d0e,0x3d0e3d55,0x3c483d7b,0xbd800000,0xbd6dbcc4,0xbd35bd35,0xbcc4bd6d,
0x3c48bd7b,0x3d0ebd55,0x3d55bd0e,0x3d7bbc48,0x3d80,0xbcc43d6d,0xbd353d35,0xbd6d3cc4,0xbd7bbc48,0xbd55bd0e,0xbd0ebd55,0xbc48bd7b,0x3d800000,0x3d6d3cc4,0x3d353d35,0x3cc43d6d,
0x80003d80,0x80003d80,0x80003d80,0x80003d80,0x8000bd80,0x8000bd80,0x8000bd80,0x8000bd80,0x80003d80,0x80003d80,0x80003d80,0x80003d80,0x8000bd80,0x8000bd80,0x8000bd80,0x8000bd80,
0x80003d80,0x80003d80,0x80003d80,0x80003d80,0x8000bd80,0x8000bd80,0x8000bd80,0x8000bd80,0x80003d80,0x80003d80,0x80003d80,0x80003d80,0x8000bd80,0x8000bd80,0x8000bd80,0x8000bd80,
0xbd35bd35,0xbd353d35,0x3d353d35,0x3d35bd35,0x80003d80,0x3d800000,0x8000bd80,0xbd800000,0xbd35bd35,0xbd353d35,0x3d353d35,0x3d35bd35,0x80003d80,0x3d800000,0x8000bd80,0xbd800000,
0xbd35bd35,0xbd353d35,0x3d353d35,0x3d35bd35,0x80003d80,0x3d800000,0x8000bd80,0xbd800000,0xbd35bd35,0xbd353d35,0x3d353d35,0x3d35bd35,0x80003d80,0x3d800000,0x8000bd80,0xbd800000,
0x3d800000,0x3d6dbcc4,0x3d35bd35,0x3cc4bd6d,0xbd7b3c48,0xbd553d0e,0xbd0e3d55,0xbc483d7b,0x80003d80,0x3cc43d6d,0x3d353d35,0x3d6d3cc4,0xbc48bd7b,0xbd0ebd55,0xbd55bd0e,0xbd7bbc48,
0xbd800000,0xbd6d3cc4,0xbd353d35,0xbcc43d6d,0x3d7bbc48,0x3d55bd0e,0x3d0ebd55,0x3c48bd7b,0x8000bd80,0xbcc4bd6d,0xbd35bd35,0xbd6dbcc4,0x3c483d7b,0x3d0e3d55,0x3d553d0e,0x3d7b3c48,
0xbd0e3d55,0x3d7b3c48,0xbc48bd7b,0xbd553d0e,0x3d800000,0xbcc4bd6d,0xbd353d35,0x3d6d3cc4,0xbd55bd0e,0xbc483d7b,0x3d7bbc48,0xbd0ebd55,0x80003d80,0x3d6dbcc4,0xbd35bd35,0xbcc43d6d,
0x3d0ebd55,0xbd7bbc48,0x3c483d7b,0x3d55bd0e,0xbd800000,0x3cc43d6d,0x3d35bd35,0xbd6dbcc4,0x3d553d0e,0x3c48bd7b,0xbd7b3c48,0x3d0e3d55,0x8000bd80,0xbd6d3cc4,0x3d353d35,0x3cc4bd6d,
0x80003d80,0x3d353d35,0x3d800000,0x3d35bd35,0xbcc4bd6d,0xbd6dbcc4,0xbd6d3cc4,0xbcc43d6d,0x8000bd80,0xbd35bd35,0xbd800000,0xbd353d35,0x3cc43d6d,0x3d6d3cc4,0x3d6dbcc4,0x3cc4bd6d,
0x80003d80,0x3d353d35,0x3d800000,0x3d35bd35,0xbcc4bd6d,0xbd6dbcc4,0xbd6d3cc4,0xbcc43d6d,0x8000bd80,0xbd35bd35,0xbd800000,0xbd353d35,0x3cc43d6d,0x3d6d3cc4,0x3d6dbcc4,0x3cc4bd6d,
0xbd6dbcc4,0x3cc43d6d,0x3cc4bd6d,0xbd6d3cc4,0x80003d80,0x3d35bd35,0xbd800000,0x3d353d35,0x3d6d3cc4,0xbcc4bd6d,0xbcc43d6d,0x3d6dbcc4,0x8000bd80,0xbd353d35,0x3d800000,0xbd35bd35,
0xbd6dbcc4,0x3cc43d6d,0x3cc4bd6d,0xbd6d3cc4,0x80003d80,0x3d35bd35,0xbd800000,0x3d353d35,0x3d6d3cc4,0xbcc4bd6d,0xbcc43d6d,0x3d6dbcc4,0x8000bd80,0xbd353d35,0x3d800000,0xbd35bd35,
0x3d800000,0x3cc4bd6d,0xbd35bd35,0xbd6d3cc4,0xbd553d0e,0x3c483d7b,0x3d7b3c48,0x3d0ebd55,0x8000bd80,0xbd6dbcc4,0xbd353d35,0x3cc43d6d,0x3d0e3d55,0x3d7bbc48,0x3c48bd7b,0xbd55bd0e,
0xbd800000,0xbcc43d6d,0x3d353d35,0x3d6dbcc4,0x3d55bd0e,0xbc48bd7b,0xbd7bbc48,0xbd0e3d55,0x80003d80,0x3d6d3cc4,0x3d35bd35,0xbcc4bd6d,0xbd0ebd55,0xbd7b3c48,0xbc483d7b,0x3d553d0e,
0xbc483d7b,0x3d0ebd55,0xbd553d0e,0x3d7bbc48,0x3d800000,0xbd6dbcc4,0x3d353d35,0xbcc4bd6d,0x3d7b3c48,0xbd55bd0e,0x3d0e3d55,0xbc48bd7b,0x8000bd80,0xbcc43d6d,0x3d35bd35,0xbd6d3cc4,
0x3c48bd7b,0xbd0e3d55,0x3d55bd0e,0xbd7b3c48,0xbd800000,0x3d6d3cc4,0xbd35bd35,0x3cc43d6d,0xbd7bbc48,0x3d553d0e,0xbd0ebd55,0x3c483d7b,0x80003d80,0x3cc4bd6d,0xbd353d35,0x3d6dbcc4,
0x3d800000,0x3d800000,0x3d800000,0x3d800000,0xbd800000,0xbd800000,0xbd800000,0xbd800000,0x3d800000,0x3d800000,0x3d800000,0x3d800000,0xbd800000,0xbd800000,0xbd800000,0xbd800000,
0x3d800000,0x3d800000,0x3d800000,0x3d800000,0xbd800000,0xbd800000,0xbd800000,0xbd800000,0x3d800000,0x3d800000,0x3d800000,0x3d800000,0xbd800000,0xbd800000,0xbd800000,0xbd800000,
0xbd353d35,0x3d353d35,0x3d35bd35,0xbd35bd35,0x3d800000,0xbd80,0xbd800000,0x3d80,0xbd353d35,0x3d353d35,0x3d35bd35,0xbd35bd35,0x3d800000,0xbd80,0xbd800000,0x3d80,
0xbd353d35,0x3d353d35,0x3d35bd35,0xbd35bd35,0x3d800000,0xbd80,0xbd800000,0x3d80,0xbd353d35,0x3d353d35,0x3d35bd35,0xbd35bd35,0x3d800000,0xbd80,0xbd800000,0x3d80,
0xbd80,0xbcc4bd6d,0xbd35bd35,0xbd6dbcc4,0x3c483d7b,0x3d0e3d55,0x3d553d0e,0x3d7b3c48,0x3d800000,0x3d6dbcc4,0x3d35bd35,0x3cc4bd6d,0xbd7b3c48,0xbd553d0e,0xbd0e3d55,0xbc483d7b,
0x3d80,0x3cc43d6d,0x3d353d35,0x3d6d3cc4,0xbc48bd7b,0xbd0ebd55,0xbd55bd0e,0xbd7bbc48,0xbd800000,0xbd6d3cc4,0xbd353d35,0xbcc43d6d,0x3d7bbc48,0x3d55bd0e,0x3d0ebd55,0x3c48bd7b,
0x3d553d0e,0x3c48bd7b,0xbd7b3c48,0x3d0e3d55,0xbd80,0xbd6d3cc4,0x3d353d35,0x3cc4bd6d,0xbd0e3d55,0x3d7b3c48,0xbc48bd7b,0xbd553d0e,0x3d800000,0xbcc4bd6d,0xbd353d35,0x3d6d3cc4,
0xbd55bd0e,0xbc483d7b,0x3d7bbc48,0xbd0ebd55,0x3d80,0x3d6dbcc4,0xbd35bd35,0xbcc43d6d,0x3d0ebd55,0xbd7bbc48,0x3c483d7b,0x3d55bd0e,0xbd800000,0x3cc43d6d,0x3d35bd35,0xbd6dbcc4,
0x3d800000,0x3d35bd35,0xbd80,0xbd35bd35,0xbd6d3cc4,0xbcc43d6d,0x3cc43d6d,0x3d6d3cc4,0xbd800000,0xbd353d35,0x3d80,0x3d353d35,0x3d6dbcc4,0x3cc4bd6d,0xbcc4bd6d,0xbd6dbcc4,
0x3d800000,0x3d35bd35,0xbd80,0xbd35bd35,0xbd6d3cc4,0xbcc43d6d,0x3cc43d6d,0x3d6d3cc4,0xbd800000,0xbd353d35,0x3d80,0x3d353d35,0x3d6dbcc4,0x3cc4bd6d,0xbcc4bd6d,0xbd6dbcc4,
0xbcc43d6d,0x3d6dbcc4,0xbd6dbcc4,0x3cc43d6d,0x3d800000,0xbd35bd35,0x3d80,0x3d35bd35,0x3cc4bd6d,0xbd6d3cc4,0x3d6d3cc4,0xbcc4bd6d,0xbd800000,0x3d353d35,0xbd80,0xbd353d35,
0xbcc43d6d,0x3d6dbcc4,0xbd6dbcc4,0x3cc43d6d,0x3d800000,0xbd35bd35,0x3d80,0x3d35bd35,0x3cc4bd6d,0xbd6d3cc4,0x3d6d3cc4,0xbcc4bd6d,0xbd800000,0x3d353d35,0xbd80,0xbd353d35,
0xbd80,0xbd6dbcc4,0xbd353d35,0x3cc43d6d,0x3d0e3d55,0x3d7bbc48,0x3c48bd7b,0xbd55bd0e,0xbd800000,0xbcc43d6d,0x3d353d35,0x3d6dbcc4,0x3d55bd0e,0xbc48bd7b,0xbd7bbc48,0xbd0e3d55,
0x3d80,0x3d6d3cc4,0x3d35bd35,0xbcc4bd6d,0xbd0ebd55,0xbd7b3c48,0xbc483d7b,0x3d553d0e,0x3d800000,0x3cc4bd6d,0xbd35bd35,0xbd6d3cc4,0xbd553d0e,0x3c483d7b,0x3d7b3c48,0x3d0ebd55,
0x3d7b3c48,0xbd55bd0e,0x3d0e3d55,0xbc48bd7b,0xbd80,0xbcc43d6d,0x3d35bd35,0xbd6d3cc4,0x3c48bd7b,0xbd0e3d55,0x3d55bd0e,0xbd7b3c48,0xbd800000,0x3d6d3cc4,0xbd35bd35,0x3cc43d6d,
0xbd7bbc48,0x3d553d0e,0xbd0ebd55,0x3c483d7b,0x3d80,0x3cc4bd6d,0xbd353d35,0x3d6dbcc4,0xbc483d7b,0x3d0ebd55,0xbd553d0e,0x3d7bbc48,0x3d800000,0xbd6dbcc4,0x3d353d35,0xbcc4bd6d,
0x80003d80,0x8000bd80,0x80003d80,0x8000bd80,0xbd800000,0x3d800000,0xbd800000,0x3d800000,0x80003d80,0x8000bd80,0x80003d80,0x8000bd80,0xbd800000,0x3d800000,0xbd800000,0x3d800000,
0x80003d80,0x8000bd80,0x80003d80,0x8000bd80,0xbd800000,0x3d800000,0xbd800000,0x3d800000,0x80003d80,0x8000bd80,0x80003d80,0x8000bd80,0xbd800000,0x3d800000,0xbd800000,0x3d800000,
0xbd353d35,0xbd35bd35,0x3d35bd35,0x3d353d35,0x80003d80,0xbd800000,0x8000bd80,0x3d800000,0xbd353d35,0xbd35bd35,0x3d35bd35,0x3d353d35,0x80003d80,0xbd800000,0x8000bd80,0x3d800000,
0xbd353d35,0xbd35bd35,0x3d35bd35,0x3d353d35,0x80003d80,0xbd800000,0x8000bd80,0x3d800000,0xbd353d35,0xbd35bd35,0x3d35bd35,0x3d353d35,0x80003d80,0xbd800000,0x8000bd80,0x3d800000,
0x3d800000,0xbd6d3cc4,0x3d35bd35,0xbcc43d6d,0x3c483d7b,0xbd0ebd55,0x3d553d0e,0xbd7bbc48,0x80003d80,0xbcc4bd6d,0x3d353d35,0xbd6dbcc4,0xbd7b3c48,0x3d55bd0e,0xbd0e3d55,0x3c48bd7b,
0xbd800000,0x3d6dbcc4,0xbd353d35,0x3cc4bd6d,0xbc48bd7b,0x3d0e3d55,0xbd55bd0e,0x3d7b3c48,0x8000bd80,0x3cc43d6d,0xbd35bd35,0x3d6d3cc4,0x3d7bbc48,0xbd553d0e,0x3d0ebd55,0xbc483d7b,
0x3d553d0e,0xbc483d7b,0xbd7b3c48,0xbd0ebd55,0x3d800000,0x3cc43d6d,0xbd353d35,0xbd6dbcc4,0xbd0e3d55,0xbd7bbc48,0xbc48bd7b,0x3d55bd0e,0x80003d80,0xbd6d3cc4,0xbd35bd35,0x3cc4bd6d,
0xbd55bd0e,0x3c48bd7b,0x3d7bbc48,0x3d0e3d55,0xbd800000,0xbcc4bd6d,0x3d35bd35,0x3d6d3cc4,0x3d0ebd55,0x3d7b3c48,0x3c483d7b,0xbd553d0e,0x8000bd80,0x3d6dbcc4,0x3d353d35,0xbcc43d6d,
0x80003d80,0xbd35bd35,0x3d800000,0xbd353d35,0xbd6d3cc4,0x3cc4bd6d,0x3cc43d6d,0xbd6dbcc4,0x8000bd80,0x3d353d35,0xbd800000,0x3d35bd35,0x3d6dbcc4,0xbcc43d6d,0xbcc4bd6d,0x3d6d3cc4,
0x80003d80,0xbd35bd35,0x3d800000,0xbd353d35,0xbd6d3cc4,0x3cc4bd6d,0x3cc43d6d,0xbd6dbcc4,0x8000bd80,0x3d353d35,0xbd800000,0x3d35bd35,0x3d6dbcc4,0xbcc43d6d,0xbcc4bd6d,0x3d6d3cc4,
0xbcc43d6d,0xbd6d3cc4,0xbd6dbcc4,0xbcc4bd6d,0x80003d80,0xbd353d35,0xbd800000,0xbd35bd35,0x3cc4bd6d,0x3d6dbcc4,0x3d6d3cc4,0x3cc43d6d,0x8000bd80,0x3d35bd35,0x3d800000,0x3d353d35,
0xbcc43d6d,0xbd6d3cc4,0xbd6dbcc4,0xbcc4bd6d,0x80003d80,0xbd353d35,0xbd800000,0xbd35bd35,0x3cc4bd6d,0x3d6dbcc4,0x3d6d3cc4,0x3cc43d6d,0x8000bd80,0x3d35bd35,0x3d800000,0x3d353d35,
0x3d800000,0xbcc43d6d,0xbd35bd35,0x3d6dbcc4,0x3d0e3d55,0xbd7b3c48,0x3c48bd7b,0x3d553d0e,0x8000bd80,0x3d6d3cc4,0xbd353d35,0xbcc4bd6d,0x3d55bd0e,0x3c483d7b,0xbd7bbc48,0x3d0ebd55,
0xbd800000,0x3cc4bd6d,0x3d353d35,0xbd6d3cc4,0xbd0ebd55,0x3d7bbc48,0xbc483d7b,0xbd55bd0e,0x80003d80,0xbd6dbcc4,0x3d35bd35,0x3cc43d6d,0xbd553d0e,0xbc48bd7b,0x3d7b3c48,0xbd0e3d55,
0x3d7b3c48,0x3d553d0e,0x3d0e3d55,0x3c483d7b,0x3d800000,0x3d6d3cc4,0x3d353d35,0x3cc43d6d,0x3c48bd7b,0x3d0ebd55,0x3d55bd0e,0x3d7bbc48,0x8000bd80,0x3cc4bd6d,0x3d35bd35,0x3d6dbcc4,
0xbd7bbc48,0xbd55bd0e,0xbd0ebd55,0xbc48bd7b,0xbd800000,0xbd6dbcc4,0xbd35bd35,0xbcc4bd6d,0xbc483d7b,0xbd0e3d55,0xbd553d0e,0xbd7b3c48,0x80003d80,0xbcc43d6d,0xbd353d35,0xbd6d3cc4,
0x3d800000,0xbd800000,0x3d800000,0xbd800000,0x3d80,0xbd80,0x3d80,0xbd80,0x3d800000,0xbd800000,0x3d800000,0xbd800000,0x3d80,0xbd80,0x3d80,0xbd80,
0x3d800000,0xbd800000,0x3d800000,0xbd800000,0x3d80,0xbd80,0x3d80,0xbd80,0x3d800000,0xbd800000,0x3d800000,0xbd800000,0x3d80,0xbd80,0x3d80,0xbd80,
0x3d353d35,0xbd353d35,0xbd35bd35,0x3d35bd35,0x3d800000,0x3d80,0xbd800000,0xbd80,0x3d353d35,0xbd353d35,0xbd35bd35,0x3d35bd35,0x3d800000,0x3d80,0xbd800000,0xbd80,
0x3d353d35,0xbd353d35,0xbd35bd35,0x3d35bd35,0x3d800000,0x3d80,0xbd800000,0xbd80,0x3d353d35,0xbd353d35,0xbd35bd35,0x3d35bd35,0x3d800000,0x3d80,0xbd800000,0xbd80,
0xbd80,0x3cc43d6d,0xbd35bd35,0x3d6d3cc4,0x3d7bbc48,0xbd553d0e,0x3d0ebd55,0xbc483d7b,0x3d800000,0xbd6d3cc4,0x3d35bd35,0xbcc43d6d,0x3c483d7b,0xbd0ebd55,0x3d553d0e,0xbd7bbc48,
0x3d80,0xbcc4bd6d,0x3d353d35,0xbd6dbcc4,0xbd7b3c48,0x3d55bd0e,0xbd0e3d55,0x3c48bd7b,0xbd800000,0x3d6dbcc4,0xbd353d35,0x3cc4bd6d,0xbc48bd7b,0x3d0e3d55,0xbd55bd0e,0x3d7b3c48,
0x3d0ebd55,0x3d7b3c48,0x3c483d7b,0xbd553d0e,0xbd80,0x3d6dbcc4,0x3d353d35,0xbcc43d6d,0x3d553d0e,0xbc483d7b,0xbd7b3c48,0xbd0ebd55,0x3d800000,0x3cc43d6d,0xbd353d35,0xbd6dbcc4,
0xbd0e3d55,0xbd7bbc48,0xbc48bd7b,0x3d55bd0e,0x3d80,0xbd6d3cc4,0xbd35bd35,0x3cc4bd6d,0xbd55bd0e,0x3c48bd7b,0x3d7bbc48,0x3d0e3d55,0xbd800000,0xbcc4bd6d,0x3d35bd35,0x3d6d3cc4,
0x3d800000,0xbd353d35,0xbd80,0x3d353d35,0x3cc43d6d,0xbd6dbcc4,0x3d6dbcc4,0xbcc43d6d,0xbd800000,0x3d35bd35,0x3d80,0xbd35bd35,0xbcc4bd6d,0x3d6d3cc4,0xbd6d3cc4,0x3cc4bd6d,
0x3d800000,0xbd353d35,0xbd80,0x3d353d35,0x3cc43d6d,0xbd6dbcc4,0x3d6dbcc4,0xbcc43d6d,0xbd800000,0x3d35bd35,0x3d80,0xbd35bd35,0xbcc4bd6d,0x3d6d3cc4,0xbd6d3cc4,0x3cc4bd6d,
0x3d6d3cc4,0x3cc43d6d,0xbcc43d6d,0xbd6d3cc4,0x3d800000,0x3d353d35,0x3d80,0xbd353d35,0xbd6dbcc4,0xbcc4bd6d,0x3cc4bd6d,0x3d6dbcc4,0xbd800000,0xbd35bd35,0xbd80,0x3d35bd35,
0x3d6d3cc4,0x3cc43d6d,0xbcc43d6d,0xbd6d3cc4,0x3d800000,0x3d353d35,0x3d80,0xbd353d35,0xbd6dbcc4,0xbcc4bd6d,0x3cc4bd6d,0x3d6dbcc4,0xbd800000,0xbd35bd35,0xbd80,0x3d35bd35,
0xbd80,0x3d6d3cc4,0xbd353d35,0xbcc4bd6d,0x3d55bd0e,0x3c483d7b,0xbd7bbc48,0x3d0ebd55,0xbd800000,0x3cc4bd6d,0x3d353d35,0xbd6d3cc4,0xbd0ebd55,0x3d7bbc48,0xbc483d7b,0xbd55bd0e,
0x3d80,0xbd6dbcc4,0x3d35bd35,0x3cc43d6d,0xbd553d0e,0xbc48bd7b,0x3d7b3c48,0xbd0e3d55,0x3d800000,0xbcc43d6d,0xbd35bd35,0x3d6dbcc4,0x3d0e3d55,0xbd7b3c48,0x3c48bd7b,0x3d553d0e,
0x3c48bd7b,0x3d0ebd55,0x3d55bd0e,0x3d7bbc48,0xbd80,0x3cc4bd6d,0x3d35bd35,0x3d6dbcc4,0xbd7bbc48,0xbd55bd0e,0xbd0ebd55,0xbc48bd7b,0xbd800000,0xbd6dbcc4,0xbd35bd35,0xbcc4bd6d,
0xbc483d7b,0xbd0e3d55,0xbd553d0e,0xbd7b3c48,0x3d80,0xbcc43d6d,0xbd353d35,0xbd6d3cc4,0x3d7b3c48,0x3d553d0e,0x3d0e3d55,0x3c483d7b,0x3d800000,0x3d6d3cc4,0x3d353d35,0x3cc43d6d,
0x3d80,0x3d80,0x3d80,0x3d80,0x3d80,0x3d80,0x3d80,0x3d80,0x3d80,0x3d80,0x3d80,0x3d80,0x3d80,0x3d80,0x3d80,0x3d80,
0x3d80,0x3d80,0x3d80,0x3d80,0x3d80,0x3d80,0x3d80,0x3d80,0x3d80,0x3d80,0x3d80,0x3d80,0x3d80,0x3d80,0x3d80,0x3d80,
0xbd353d35,0xbd553d0e,0xbd6d3cc4,0xbd7b3c48,0x3d80,0xbc483d7b,0xbcc43d6d,0xbd0e3d55,0xbd35bd35,0xbd0ebd55,0xbcc4bd6d,0xbc48bd7b,0xbd800000,0xbd7bbc48,0xbd6dbcc4,0xbd55bd0e,
0x3d35bd35,0x3d55bd0e,0x3d6dbcc4,0x3d7bbc48,0xbd80,0x3c48bd7b,0x3cc4bd6d,0x3d0ebd55,0x3d353d35,0x3d0e3d55,0x3cc43d6d,0x3c483d7b,0x3d800000,0x3d7b3c48,0x3d6d3cc4,0x3d553d0e,
0xbd80,0x3cc4bd6d,0x3d35bd35,0x3d6dbcc4,0x3d800000,0x3d6d3cc4,0x3d353d35,0x3cc43d6d,0x3d80,0xbcc43d6d,0xbd353d35,0xbd6d3cc4,0xbd800000,0xbd6dbcc4,0xbd35bd35,0xbcc4bd6d,
0xbd80,0x3cc4bd6d,0x3d35bd35,0x3d6dbcc4,0x3d800000,0x3d6d3cc4,0x3d353d35,0x3cc43d6d,0x3d80,0xbcc43d6d,0xbd353d35,0xbd6d3cc4,0xbd800000,0xbd6dbcc4,0xbd35bd35,0xbcc4bd6d,
0xbd353d35,0xbd7b3c48,0xbd6dbcc4,0xbd0ebd55,0x3d800000,0x3d553d0e,0x3cc43d6d,0xbc483d7b,0xbd35bd35,0xbc48bd7b,0x3cc4bd6d,0x3d55bd0e,0x3d80,0xbd0e3d55,0xbd6d3cc4,0xbd7bbc48,
0x3d35bd35,0x3d7bbc48,0x3d6d3cc4,0x3d0e3d55,0xbd800000,0xbd55bd0e,0xbcc4bd6d,0x3c48bd7b,0x3d353d35,0x3c483d7b,0xbcc43d6d,0xbd553d0e,0xbd80,0x3d0ebd55,0x3d6dbcc4,0x3d7b3c48,
0x3d80,0xbd353d35,0xbd800000,0xbd35bd35,0xbd80,0x3d35bd35,0x3d800000,0x3d353d35,0x3d80,0xbd353d35,0xbd800000,0xbd35bd35,0xbd80,0x3d35bd35,0x3d800000,0x3d353d35,
0x3d80,0xbd353d35,0xbd800000,0xbd35bd35,0xbd80,0x3d35bd35,0x3d800000,0x3d353d35,0x3d80,0xbd353d35,0xbd800000,0xbd35bd35,0xbd80,0x3d35bd35,0x3d800000,0x3d353d35,
0xbd353d35,0xbd7bbc48,0xbcc4bd6d,0x3d0ebd55,0xbd80,0x3d55bd0e,0x3d6d3cc4,0x3c483d7b,0xbd35bd35,0x3c48bd7b,0x3d6dbcc4,0x3d553d0e,0x3d800000,0x3d0e3d55,0xbcc43d6d,0xbd7b3c48,
0x3d35bd35,0x3d7b3c48,0x3cc43d6d,0xbd0e3d55,0x3d80,0xbd553d0e,0xbd6dbcc4,0xbc48bd7b,0x3d353d35,0xbc483d7b,0xbd6d3cc4,0xbd55bd0e,0xbd800000,0xbd0ebd55,0x3cc4bd6d,0x3d7bbc48,
0xbd80,0x3d6dbcc4,0x3d353d35,0xbcc43d6d,0xbd800000,0xbcc4bd6d,0x3d35bd35,0x3d6d3cc4,0x3d80,0xbd6d3cc4,0xbd35bd35,0x3cc4bd6d,0x3d800000,0x3cc43d6d,0xbd353d35,0xbd6dbcc4,
0xbd80,0x3d6dbcc4,0x3d353d35,0xbcc43d6d,0xbd800000,0xbcc4bd6d,0x3d35bd35,0x3d6d3cc4,0x3d80,0xbd6d3cc4,0xbd35bd35,0x3cc4bd6d,0x3d800000,0x3cc43d6d,0xbd353d35,0xbd6dbcc4,
0xbd353d35,0xbd55bd0e,0x3cc4bd6d,0x3d7b3c48,0xbd800000,0xbc48bd7b,0x3d6dbcc4,0x3d0e3d55,0xbd35bd35,0x3d0ebd55,0x3d6d3cc4,0xbc483d7b,0xbd80,0x3d7bbc48,0x3cc43d6d,0xbd553d0e,
0x3d35bd35,0x3d553d0e,0xbcc43d6d,0xbd7bbc48,0x3d800000,0x3c483d7b,0xbd6d3cc4,0xbd0ebd55,0x3d353d35,0xbd0e3d55,0xbd6dbcc4,0x3c48bd7b,0x3d80,0xbd7b3c48,0xbcc4bd6d,0x3d55bd0e,
0xbd800000,0xbd800000,0xbd800000,0xbd800000,0xbd800000,0xbd800000,0xbd800000,0xbd800000,0xbd800000,0xbd800000,0xbd800000,0xbd800000,0xbd800000,0xbd800000,0xbd800000,0xbd800000,
0xbd800000,0xbd800000,0xbd800000,0xbd800000,0xbd800000,0xbd800000,0xbd800000,0xbd800000,0xbd800000,0xbd800000,0xbd800000,0xbd800000,0xbd800000,0xbd800000,0xbd800000,0xbd800000,
0xbd35bd35,0xbd0ebd55,0xbcc4bd6d,0xbc48bd7b,0xbd800000,0xbd7bbc48,0xbd6dbcc4,0xbd55bd0e,0x3d35bd35,0x3d55bd0e,0x3d6dbcc4,0x3d7bbc48,0x8000bd80,0x3c48bd7b,0x3cc4bd6d,0x3d0ebd55,
0x3d353d35,0x3d0e3d55,0x3cc43d6d,0x3c483d7b,0x3d800000,0x3d7b3c48,0x3d6d3cc4,0x3d553d0e,0xbd353d35,0xbd553d0e,0xbd6d3cc4,0xbd7b3c48,0x80003d80,0xbc483d7b,0xbcc43d6d,0xbd0e3d55,
0x3d800000,0x3d6d3cc4,0x3d353d35,0x3cc43d6d,0x80003d80,0xbcc43d6d,0xbd353d35,0xbd6d3cc4,0xbd800000,0xbd6dbcc4,0xbd35bd35,0xbcc4bd6d,0x8000bd80,0x3cc4bd6d,0x3d35bd35,0x3d6dbcc4,
0x3d800000,0x3d6d3cc4,0x3d353d35,0x3cc43d6d,0x80003d80,0xbcc43d6d,0xbd353d35,0xbd6d3cc4,0xbd800000,0xbd6dbcc4,0xbd35bd35,0xbcc4bd6d,0x8000bd80,0x3cc4bd6d,0x3d35bd35,0x3d6dbcc4,
0xbd35bd35,0xbc48bd7b,0x3cc4bd6d,0x3d55bd0e,0x80003d80,0xbd0e3d55,0xbd6d3cc4,0xbd7bbc48,0x3d35bd35,0x3d7bbc48,0x3d6d3cc4,0x3d0e3d55,0xbd800000,0xbd55bd0e,0xbcc4bd6d,0x3c48bd7b,
0x3d353d35,0x3c483d7b,0xbcc43d6d,0xbd553d0e,0x8000bd80,0x3d0ebd55,0x3d6dbcc4,0x3d7b3c48,0xbd353d35,0xbd7b3c48,0xbd6dbcc4,0xbd0ebd55,0x3d800000,0x3d553d0e,0x3cc43d6d,0xbc483d7b,
0xbd800000,0xbd35bd35,0x8000bd80,0x3d35bd35,0x3d800000,0x3d353d35,0x80003d80,0xbd353d35,0xbd800000,0xbd35bd35,0x8000bd80,0x3d35bd35,0x3d800000,0x3d353d35,0x80003d80,0xbd353d35,
0xbd800000,0xbd35bd35,0x8000bd80,0x3d35bd35,0x3d800000,0x3d353d35,0x80003d80,0xbd353d35,0xbd800000,0xbd35bd35,0x8000bd80,0x3d35bd35,0x3d800000,0x3d353d35,0x80003d80,0xbd353d35,
0xbd35bd35,0x3c48bd7b,0x3d6dbcc4,0x3d553d0e,0x3d800000,0x3d0e3d55,0xbcc43d6d,0xbd7b3c48,0x3d35bd35,0x3d7b3c48,0x3cc43d6d,0xbd0e3d55,0x80003d80,0xbd553d0e,0xbd6dbcc4,0xbc48bd7b,
0x3d353d35,0xbc483d7b,0xbd6d3cc4,0xbd55bd0e,0xbd800000,0xbd0ebd55,0x3cc4bd6d,0x3d7bbc48,0xbd353d35,0xbd7bbc48,0xbcc4bd6d,0x3d0ebd55,0x8000bd80,0x3d55bd0e,0x3d6d3cc4,0x3c483d7b,
0x3d800000,0x3cc43d6d,0xbd353d35,0xbd6dbcc4,0x8000bd80,0x3d6dbcc4,0x3d353d35,0xbcc43d6d,0xbd800000,0xbcc4bd6d,0x3d35bd35,0x3d6d3cc4,0x80003d80,0xbd6d3cc4,0xbd35bd35,0x3cc4bd6d,
0x3d800000,0x3cc43d6d,0xbd353d35,0xbd6dbcc4,0x8000bd80,0x3d6dbcc4,0x3d353d35,0xbcc43d6d,0xbd800000,0xbcc4bd6d,0x3d35bd35,0x3d6d3cc4,0x80003d80,0xbd6d3cc4,0xbd35bd35,0x3cc4bd6d,
0xbd35bd35,0x3d0ebd55,0x3d6d3cc4,0xbc483d7b,0x8000bd80,0x3d7bbc48,0x3cc43d6d,0xbd553d0e,0x3d35bd35,0x3d553d0e,0xbcc43d6d,0xbd7bbc48,0x3d800000,0x3c483d7b,0xbd6d3cc4,0xbd0ebd55,
0x3d353d35,0xbd0e3d55,0xbd6dbcc4,0x3c48bd7b,0x80003d80,0xbd7b3c48,0xbcc4bd6d,0x3d55bd0e,0xbd353d35,0xbd55bd0e,0x3cc4bd6d,0x3d7b3c48,0xbd800000,0xbc48bd7b,0x3d6dbcc4,0x3d0e3d55,
0x3d80,0xbd800000,0xbd80,0x3d800000,0x3d80,0xbd800000,0xbd80,0x3d800000,0x3d80,0xbd800000,0xbd80,0x3d800000,0x3d80,0xbd800000,0xbd80,0x3d800000,
0x3d80,0xbd800000,0xbd80,0x3d800000,0x3d80,0xbd800000,0xbd80,0x3d800000,0x3d80,0xbd800000,0xbd80,0x3d800000,0x3d80,0xbd800000,0xbd80,0x3d800000,
0xbd353d35,0xbd0ebd55,0x3d6dbcc4,0x3c483d7b,0x3d80,0xbd7bbc48,0x3cc4bd6d,0x3d553d0e,0xbd35bd35,0x3d55bd0e,0x3cc43d6d,0xbd7b3c48,0xbd800000,0x3c48bd7b,0x3d6d3cc4,0xbd0e3d55,
0x3d35bd35,0x3d0e3d55,0xbd6d3cc4,0xbc48bd7b,0xbd80,0x3d7b3c48,0xbcc43d6d,0xbd55bd0e,0x3d353d35,0xbd553d0e,0xbcc4bd6d,0x3d7bbc48,0x3d800000,0xbc483d7b,0xbd6dbcc4,0x3d0ebd55,
0xbd80,0x3d6d3cc4,0xbd353d35,0xbcc4bd6d,0x3d800000,0xbcc43d6d,0xbd35bd35,0x3d6dbcc4,0x3d80,0xbd6dbcc4,0x3d35bd35,0x3cc43d6d,0xbd800000,0x3cc4bd6d,0x3d353d35,0xbd6d3cc4,
0xbd80,0x3d6d3cc4,0xbd353d35,0xbcc4bd6d,0x3d800000,0xbcc43d6d,0xbd35bd35,0x3d6dbcc4,0x3d80,0xbd6dbcc4,0x3d35bd35,0x3cc43d6d,0xbd800000,0x3cc4bd6d,0x3d353d35,0xbd6d3cc4,
0xbd353d35,0xbc48bd7b,0x3d6d3cc4,0xbd553d0e,0x3d800000,0xbd0e3d55,0xbcc4bd6d,0x3d7b3c48,0xbd35bd35,0x3d7bbc48,0xbcc43d6d,0xbd0ebd55,0x3d80,0xbd55bd0e,0x3d6dbcc4,0xbc483d7b,
0x3d35bd35,0x3c483d7b,0xbd6dbcc4,0x3d55bd0e,0xbd800000,0x3d0ebd55,0x3cc43d6d,0xbd7bbc48,0x3d353d35,0xbd7b3c48,0x3cc4bd6d,0x3d0e3d55,0xbd80,0x3d553d0e,0xbd6d3cc4,0x3c48bd7b,
0x3d80,0xbd35bd35,0x3d800000,0xbd353d35,0xbd80,0x3d353d35,0xbd800000,0x3d35bd35,0x3d80,0xbd35bd35,0x3d800000,0xbd353d35,0xbd80,0x3d353d35,0xbd800000,0x3d35bd35,
0x3d80,0xbd35bd35,0x3d800000,0xbd353d35,0xbd80,0x3d353d35,0xbd800000,0x3d35bd35,0x3d80,0xbd35bd35,0x3d800000,0xbd353d35,0xbd80,0x3d353d35,0xbd800000,0x3d35bd35,
0xbd353d35,0x3c48bd7b,0x3cc43d6d,0xbd55bd0e,0xbd80,0x3d0e3d55,0xbd6dbcc4,0x3d7bbc48,0xbd35bd35,0x3d7b3c48,0xbd6d3cc4,0x3d0ebd55,0x3d800000,0xbd553d0e,0x3cc4bd6d,0x3c483d7b,
0x3d35bd35,0xbc483d7b,0xbcc4bd6d,0x3d553d0e,0x3d80,0xbd0ebd55,0x3d6d3cc4,0xbd7b3c48,0x3d353d35,0xbd7bbc48,0x3d6dbcc4,0xbd0e3d55,0xbd800000,0x3d55bd0e,0xbcc43d6d,0xbc48bd7b,
0xbd80,0x3cc43d6d,0xbd35bd35,0x3d6d3cc4,0xbd800000,0x3d6dbcc4,0xbd353d35,0x3cc4bd6d,0x3d80,0xbcc4bd6d,0x3d353d35,0xbd6dbcc4,0x3d800000,0xbd6d3cc4,0x3d35bd35,0xbcc43d6d,
0xbd80,0x3cc43d6d,0xbd35bd35,0x3d6d3cc4,0xbd800000,0x3d6dbcc4,0xbd353d35,0x3cc4bd6d,0x3d80,0xbcc4bd6d,0x3d353d35,0xbd6dbcc4,0x3d800000,0xbd6d3cc4,0x3d35bd35,0xbcc43d6d,
0xbd353d35,0x3d0ebd55,0xbcc43d6d,0x3c48bd7b,0xbd800000,0x3d7bbc48,0xbd6d3cc4,0x3d55bd0e,0xbd35bd35,0x3d553d0e,0xbd6dbcc4,0x3d7b3c48,0xbd80,0x3c483d7b,0xbcc4bd6d,0x3d0e3d55,
0x3d35bd35,0xbd0e3d55,0x3cc4bd6d,0xbc483d7b,0x3d800000,0xbd7b3c48,0x3d6dbcc4,0xbd553d0e,0x3d353d35,0xbd55bd0e,0x3d6d3cc4,0xbd7bbc48,0x3d80,0xbc48bd7b,0x3cc43d6d,0xbd0ebd55,
0xbd800000,0x8000bd80,0x3d800000,0x80003d80,0xbd800000,0x8000bd80,0x3d800000,0x80003d80,0xbd800000,0x8000bd80,0x3d800000,0x80003d80,0xbd800000,0x8000bd80,0x3d800000,0x80003d80,
0xbd800000,0x8000bd80,0x3d800000,0x80003d80,0xbd800000,0x8000bd80,0x3d800000,0x80003d80,0xbd800000,0x8000bd80,0x3d800000,0x80003d80,0xbd800000,0x8000bd80,0x3d800000,0x80003d80,
0xbd35bd35,0x3d55bd0e,0x3cc43d6d,0xbd7b3c48,0xbd800000,0x3c48bd7b,0x3d6d3cc4,0xbd0e3d55,0x3d35bd35,0x3d0e3d55,0xbd6d3cc4,0xbc48bd7b,0x8000bd80,0x3d7b3c48,0xbcc43d6d,0xbd55bd0e,
0x3d353d35,0xbd553d0e,0xbcc4bd6d,0x3d7bbc48,0x3d800000,0xbc483d7b,0xbd6dbcc4,0x3d0ebd55,0xbd353d35,0xbd0ebd55,0x3d6dbcc4,0x3c483d7b,0x80003d80,0xbd7bbc48,0x3cc4bd6d,0x3d553d0e,
0x3d800000,0xbcc43d6d,0xbd35bd35,0x3d6dbcc4,0x80003d80,0xbd6dbcc4,0x3d35bd35,0x3cc43d6d,0xbd800000,0x3cc4bd6d,0x3d353d35,0xbd6d3cc4,0x8000bd80,0x3d6d3cc4,0xbd353d35,0xbcc4bd6d,
0x3d800000,0xbcc43d6d,0xbd35bd35,0x3d6dbcc4,0x80003d80,0xbd6dbcc4,0x3d35bd35,0x3cc43d6d,0xbd800000,0x3cc4bd6d,0x3d353d35,0xbd6d3cc4,0x8000bd80,0x3d6d3cc4,0xbd353d35,0xbcc4bd6d,
0xbd35bd35,0x3d7bbc48,0xbcc43d6d,0xbd0ebd55,0x80003d80,0xbd55bd0e,0x3d6dbcc4,0xbc483d7b,0x3d35bd35,0x3c483d7b,0xbd6dbcc4,0x3d55bd0e,0xbd800000,0x3d0ebd55,0x3cc43d6d,0xbd7bbc48,
0x3d353d35,0xbd7b3c48,0x3cc4bd6d,0x3d0e3d55,0x8000bd80,0x3d553d0e,0xbd6d3cc4,0x3c48bd7b,0xbd353d35,0xbc48bd7b,0x3d6d3cc4,0xbd553d0e,0x3d800000,0xbd0e3d55,0xbcc4bd6d,0x3d7b3c48,
0xbd800000,0x3d35bd35,0x80003d80,0xbd35bd35,0x3d800000,0xbd353d35,0x8000bd80,0x3d353d35,0xbd800000,0x3d35bd35,0x80003d80,0xbd35bd35,0x3d800000,0xbd353d35,0x8000bd80,0x3d353d35,
0xbd800000,0x3d35bd35,0x80003d80,0xbd35bd35,0x3d800000,0xbd353d35,0x8000bd80,0x3d353d35,0xbd800000,0x3d35bd35,0x80003d80,0xbd35bd35,0x3d800000,0xbd353d35,0x8000bd80,0x3d353d35,
0xbd35bd35,0x3d7b3c48,0xbd6d3cc4,0x3d0ebd55,0x3d800000,0xbd553d0e,0x3cc4bd6d,0x3c483d7b,0x3d35bd35,0xbc483d7b,0xbcc4bd6d,0x3d553d0e,0x80003d80,0xbd0ebd55,0x3d6d3cc4,0xbd7b3c48,
0x3d353d35,0xbd7bbc48,0x3d6dbcc4,0xbd0e3d55,0xbd800000,0x3d55bd0e,0xbcc43d6d,0xbc48bd7b,0xbd353d35,0x3c48bd7b,0x3cc43d6d,0xbd55bd0e,0x8000bd80,0x3d0e3d55,0xbd6dbcc4,0x3d7bbc48,
0x3d800000,0xbd6d3cc4,0x3d35bd35,0xbcc43d6d,0x8000bd80,0x3cc43d6d,0xbd35bd35,0x3d6d3cc4,0xbd800000,0x3d6dbcc4,0xbd353d35,0x3cc4bd6d,0x80003d80,0xbcc4bd6d,0x3d353d35,0xbd6dbcc4,
0x3d800000,0xbd6d3cc4,0x3d35bd35,0xbcc43d6d,0x8000bd80,0x3cc43d6d,0xbd35bd35,0x3d6d3cc4,0xbd800000,0x3d6dbcc4,0xbd353d35,0x3cc4bd6d,0x80003d80,0xbcc4bd6d,0x3d353d35,0xbd6dbcc4,
0xbd35bd35,0x3d553d0e,0xbd6dbcc4,0x3d7b3c48,0x8000bd80,0x3c483d7b,0xbcc4bd6d,0x3d0e3d55,0x3d35bd35,0xbd0e3d55,0x3cc4bd6d,0xbc483d7b,0x3d800000,0xbd7b3c48,0x3d6dbcc4,0xbd553d0e,
0x3d353d35,0xbd55bd0e,0x3d6d3cc4,0xbd7bbc48,0x80003d80,0xbc48bd7b,0x3cc43d6d,0xbd0ebd55,0xbd353d35,0x3d0ebd55,0xbcc43d6d,0x3c48bd7b,0xbd800000,0x3d7bbc48,0xbd6d3cc4,0x3d55bd0e,
0x3d80,0xbd80,0x3d80,0xbd80,0x3d80,0xbd80,0x3d80,0xbd80,0x3d80,0xbd80,0x3d80,0xbd80,0x3d80,0xbd80,0x3d80,0xbd80,
0x3d80,0xbd80,0x3d80,0xbd80,0x3d80,0xbd80,0x3d80,0xbd80,0x3d80,0xbd80,0x3d80,0xbd80,0x3d80,0xbd80,0x3d80,0xbd80,
0xbd353d35,0x3d55bd0e,0xbd6d3cc4,0x3d7bbc48,0x3d80,0x3c48bd7b,0xbcc43d6d,0x3d0ebd55,0xbd35bd35,0x3d0e3d55,0xbcc4bd6d,0x3c483d7b,0xbd800000,0x3d7b3c48,0xbd6dbcc4,0x3d553d0e,
0x3d35bd35,0xbd553d0e,0x3d6dbcc4,0xbd7b3c48,0xbd80,0xbc483d7b,0x3cc4bd6d,0xbd0e3d55,0x3d353d35,0xbd0ebd55,0x3cc43d6d,0xbc48bd7b,0x3d800000,0xbd7bbc48,0x3d6d3cc4,0xbd55bd0e,
0xbd80,0xbcc43d6d,0x3d35bd35,0xbd6d3cc4,0x3d800000,0xbd6dbcc4,0x3d353d35,0xbcc4bd6d,0x3d80,0x3cc4bd6d,0xbd353d35,0x3d6dbcc4,0xbd800000,0x3d6d3cc4,0xbd35bd35,0x3cc43d6d,
0xbd80,0xbcc43d6d,0x3d35bd35,0xbd6d3cc4,0x3d800000,0xbd6dbcc4,0x3d353d35,0xbcc4bd6d,0x3d80,0x3cc4bd6d,0xbd353d35,0x3d6dbcc4,0xbd800000,0x3d6d3cc4,0xbd35bd35,0x3cc43d6d,
0xbd353d35,0x3d7bbc48,0xbd6dbcc4,0x3d0e3d55,0x3d800000,0xbd55bd0e,0x3cc43d6d,0x3c48bd7b,0xbd35bd35,0x3c483d7b,0x3cc4bd6d,0xbd553d0e,0x3d80,0x3d0ebd55,0xbd6d3cc4,0x3d7b3c48,
0x3d35bd35,0xbd7b3c48,0x3d6d3cc4,0xbd0ebd55,0xbd800000,0x3d553d0e,0xbcc4bd6d,0xbc483d7b,0x3d353d35,0xbc48bd7b,0xbcc43d6d,0x3d55bd0e,0xbd80,0xbd0e3d55,0x3d6dbcc4,0xbd7bbc48,
0x3d80,0x3d35bd35,0xbd800000,0x3d353d35,0xbd80,0xbd353d35,0x3d800000,0xbd35bd35,0x3d80,0x3d35bd35,0xbd800000,0x3d353d35,0xbd80,0xbd353d35,0x3d800000,0xbd35bd35,
0x3d80,0x3d35bd35,0xbd800000,0x3d353d35,0xbd80,0xbd353d35,0x3d800000,0xbd35bd35,0x3d80,0x3d35bd35,0xbd800000,0x3d353d35,0xbd80,0xbd353d35,0x3d800000,0xbd35bd35,
0xbd353d35,0x3d7b3c48,0xbcc4bd6d,0xbd0e3d55,0xbd80,0xbd553d0e,0x3d6d3cc4,0xbc48bd7b,0xbd35bd35,0xbc483d7b,0x3d6dbcc4,0xbd55bd0e,0x3d800000,0xbd0ebd55,0xbcc43d6d,0x3d7bbc48,
0x3d35bd35,0xbd7bbc48,0x3cc43d6d,0x3d0ebd55,0x3d80,0x3d55bd0e,0xbd6dbcc4,0x3c483d7b,0x3d353d35,0x3c48bd7b,0xbd6d3cc4,0x3d553d0e,0xbd800000,0x3d0e3d55,0x3cc4bd6d,0xbd7b3c48,
0xbd80,0xbd6d3cc4,0x3d353d35,0x3cc4bd6d,0xbd800000,0x3cc43d6d,0x3d35bd35,0xbd6dbcc4,0x3d80,0x3d6dbcc4,0xbd35bd35,0xbcc43d6d,0x3d800000,0xbcc4bd6d,0xbd353d35,0x3d6d3cc4,
0xbd80,0xbd6d3cc4,0x3d353d35,0x3cc4bd6d,0xbd800000,0x3cc43d6d,0x3d35bd35,0xbd6dbcc4,0x3d80,0x3d6dbcc4,0xbd35bd35,0xbcc43d6d,0x3d800000,0xbcc4bd6d,0xbd353d35,0x3d6d3cc4,
0xbd353d35,0x3d553d0e,0x3cc4bd6d,0xbd7bbc48,0xbd800000,0x3c483d7b,0x3d6dbcc4,0xbd0ebd55,0xbd35bd35,0xbd0e3d55,0x3d6d3cc4,0x3c48bd7b,0xbd80,0xbd7b3c48,0x3cc43d6d,0x3d55bd0e,
0x3d35bd35,0xbd55bd0e,0xbcc43d6d,0x3d7b3c48,0x3d800000,0xbc48bd7b,0xbd6d3cc4,0x3d0e3d55,0x3d353d35,0x3d0ebd55,0xbd6dbcc4,0xbc483d7b,0x3d80,0x3d7bbc48,0xbcc4bd6d,0xbd553d0e,
0xbd800000,0x3d800000,0xbd800000,0x3d800000,0xbd800000,0x3d800000,0xbd800000,0x3d800000,0xbd800000,0x3d800000,0xbd800000,0x3d800000,0xbd800000,0x3d800000,0xbd800000,0x3d800000,
0xbd800000,0x3d800000,0xbd800000,0x3d800000,0xbd800000,0x3d800000,0xbd800000,0x3d800000,0xbd800000,0x3d800000,0xbd800000,0x3d800000,0xbd800000,0x3d800000,0xbd800000,0x3d800000,
0xbd35bd35,0x3d0e3d55,0xbcc4bd6d,0x3c483d7b,0xbd800000,0x3d7b3c48,0xbd6dbcc4,0x3d553d0e,0x3d35bd35,0xbd553d0e,0x3d6dbcc4,0xbd7b3c48,0x8000bd80,0xbc483d7b,0x3cc4bd6d,0xbd0e3d55,
0x3d353d35,0xbd0ebd55,0x3cc43d6d,0xbc48bd7b,0x3d800000,0xbd7bbc48,0x3d6d3cc4,0xbd55bd0e,0xbd353d35,0x3d55bd0e,0xbd6d3cc4,0x3d7bbc48,0x80003d80,0x3c48bd7b,0xbcc43d6d,0x3d0ebd55,
0x3d800000,0xbd6dbcc4,0x3d353d35,0xbcc4bd6d,0x80003d80,0x3cc4bd6d,0xbd353d35,0x3d6dbcc4,0xbd800000,0x3d6d3cc4,0xbd35bd35,0x3cc43d6d,0x8000bd80,0xbcc43d6d,0x3d35bd35,0xbd6d3cc4,
0x3d800000,0xbd6dbcc4,0x3d353d35,0xbcc4bd6d,0x80003d80,0x3cc4bd6d,0xbd353d35,0x3d6dbcc4,0xbd800000,0x3d6d3cc4,0xbd35bd35,0x3cc43d6d,0x8000bd80,0xbcc43d6d,0x3d35bd35,0xbd6d3cc4,
0xbd35bd35,0x3c483d7b,0x3cc4bd6d,0xbd553d0e,0x80003d80,0x3d0ebd55,0xbd6d3cc4,0x3d7b3c48,0x3d35bd35,0xbd7b3c48,0x3d6d3cc4,0xbd0ebd55,0xbd800000,0x3d553d0e,0xbcc4bd6d,0xbc483d7b,
0x3d353d35,0xbc48bd7b,0xbcc43d6d,0x3d55bd0e,0x8000bd80,0xbd0e3d55,0x3d6dbcc4,0xbd7bbc48,0xbd353d35,0x3d7bbc48,0xbd6dbcc4,0x3d0e3d55,0x3d800000,0xbd55bd0e,0x3cc43d6d,0x3c48bd7b,
0xbd800000,0x3d353d35,0x8000bd80,0xbd353d35,0x3d800000,0xbd35bd35,0x80003d80,0x3d35bd35,0xbd800000,0x3d353d35,0x8000bd80,0xbd353d35,0x3d800000,0xbd35bd35,0x80003d80,0x3d35bd35,
0xbd800000,0x3d353d35,0x8000bd80,0xbd353d35,0x3d800000,0xbd35bd35,0x80003d80,0x3d35bd35,0xbd800000,0x3d353d35,0x8000bd80,0xbd353d35,0x3d800000,0xbd35bd35,0x80003d80,0x3d35bd35,
0xbd35bd35,0xbc483d7b,0x3d6dbcc4,0xbd55bd0e,0x3d800000,0xbd0ebd55,0xbcc43d6d,0x3d7bbc48,0x3d35bd35,0xbd7bbc48,0x3cc43d6d,0x3d0ebd55,0x80003d80,0x3d55bd0e,0xbd6dbcc4,0x3c483d7b,
0x3d353d35,0x3c48bd7b,0xbd6d3cc4,0x3d553d0e,0xbd800000,0x3d0e3d55,0x3cc4bd6d,0xbd7b3c48,0xbd353d35,0x3d7b3c48,0xbcc4bd6d,0xbd0e3d55,0x8000bd80,0xbd553d0e,0x3d6d3cc4,0xbc48bd7b,
0x3d800000,0xbcc4bd6d,0xbd353d35,0x3d6d3cc4,0x8000bd80,0xbd6d3cc4,0x3d353d35,0x3cc4bd6d,0xbd800000,0x3cc43d6d,0x3d35bd35,0xbd6dbcc4,0x80003d80,0x3d6dbcc4,0xbd35bd35,0xbcc43d6d,
0x3d800000,0xbcc4bd6d,0xbd353d35,0x3d6d3cc4,0x8000bd80,0xbd6d3cc4,0x3d353d35,0x3cc4bd6d,0xbd800000,0x3cc43d6d,0x3d35bd35,0xbd6dbcc4,0x80003d80,0x3d6dbcc4,0xbd35bd35,0xbcc43d6d,
0xbd35bd35,0xbd0e3d55,0x3d6d3cc4,0x3c48bd7b,0x8000bd80,0xbd7b3c48,0x3cc43d6d,0x3d55bd0e,0x3d35bd35,0xbd55bd0e,0xbcc43d6d,0x3d7b3c48,0x3d800000,0xbc48bd7b,0xbd6d3cc4,0x3d0e3d55,
0x3d353d35,0x3d0ebd55,0xbd6dbcc4,0xbc483d7b,0x80003d80,0x3d7bbc48,0xbcc4bd6d,0xbd553d0e,0xbd353d35,0x3d553d0e,0x3cc4bd6d,0xbd7bbc48,0xbd800000,0x3c483d7b,0x3d6dbcc4,0xbd0ebd55,
0x3d80,0x3d800000,0xbd80,0xbd800000,0x3d80,0x3d800000,0xbd80,0xbd800000,0x3d80,0x3d800000,0xbd80,0xbd800000,0x3d80,0x3d800000,0xbd80,0xbd800000,
0x3d80,0x3d800000,0xbd80,0xbd800000,0x3d80,0x3d800000,0xbd80,0xbd800000,0x3d80,0x3d800000,0xbd80,0xbd800000,0x3d80,0x3d800000,0xbd80,0xbd800000,
0xbd353d35,0x3d0e3d55,0x3d6dbcc4,0xbc48bd7b,0x3d80,0x3d7b3c48,0x3cc4bd6d,0xbd55bd0e,0xbd35bd35,0xbd553d0e,0x3cc43d6d,0x3d7bbc48,0xbd800000,0xbc483d7b,0x3d6d3cc4,0x3d0ebd55,
0x3d35bd35,0xbd0ebd55,0xbd6d3cc4,0x3c483d7b,0xbd80,0xbd7bbc48,0xbcc43d6d,0x3d553d0e,0x3d353d35,0x3d55bd0e,0xbcc4bd6d,0xbd7b3c48,0x3d800000,0x3c48bd7b,0xbd6dbcc4,0xbd0e3d55,
0xbd80,0xbd6dbcc4,0xbd353d35,0x3cc43d6d,0x3d800000,0x3cc4bd6d,0xbd35bd35,0xbd6d3cc4,0x3d80,0x3d6d3cc4,0x3d35bd35,0xbcc4bd6d,0xbd800000,0xbcc43d6d,0x3d353d35,0x3d6dbcc4,
0xbd80,0xbd6dbcc4,0xbd353d35,0x3cc43d6d,0x3d800000,0x3cc4bd6d,0xbd35bd35,0xbd6d3cc4,0x3d80,0x3d6d3cc4,0x3d35bd35,0xbcc4bd6d,0xbd800000,0xbcc43d6d,0x3d353d35,0x3d6dbcc4,
0xbd353d35,0x3c483d7b,0x3d6d3cc4,0x3d55bd0e,0x3d800000,0x3d0ebd55,0xbcc4bd6d,0xbd7bbc48,0xbd35bd35,0xbd7b3c48,0xbcc43d6d,0x3d0e3d55,0x3d80,0x3d553d0e,0x3d6dbcc4,0x3c48bd7b,
0x3d35bd35,0xbc48bd7b,0xbd6dbcc4,0xbd553d0e,0xbd800000,0xbd0e3d55,0x3cc43d6d,0x3d7b3c48,0x3d353d35,0x3d7bbc48,0x3cc4bd6d,0xbd0ebd55,0xbd80,0xbd55bd0e,0xbd6d3cc4,0xbc483d7b,
0x3d80,0x3d353d35,0x3d800000,0x3d35bd35,0xbd80,0xbd35bd35,0xbd800000,0xbd353d35,0x3d80,0x3d353d35,0x3d800000,0x3d35bd35,0xbd80,0xbd35bd35,0xbd800000,0xbd353d35,
0x3d80,0x3d353d35,0x3d800000,0x3d35bd35,0xbd80,0xbd35bd35,0xbd800000,0xbd353d35,0x3d80,0x3d353d35,0x3d800000,0x3d35bd35,0xbd80,0xbd35bd35,0xbd800000,0xbd353d35,
0xbd353d35,0xbc483d7b,0x3cc43d6d,0x3d553d0e,0xbd80,0xbd0ebd55,0xbd6dbcc4,0xbd7b3c48,0xbd35bd35,0xbd7bbc48,0xbd6d3cc4,0xbd0e3d55,0x3d800000,0x3d55bd0e,0x3cc4bd6d,0xbc48bd7b,
0x3d35bd35,0x3c48bd7b,0xbcc4bd6d,0xbd55bd0e,0x3d80,0x3d0e3d55,0x3d6d3cc4,0x3d7bbc48,0x3d353d35,0x3d7b3c48,0x3d6dbcc4,0x3d0ebd55,0xbd800000,0xbd553d0e,0xbcc43d6d,0x3c483d7b,
0xbd80,0xbcc4bd6d,0xbd35bd35,0xbd6dbcc4,0xbd800000,0xbd6d3cc4,0xbd353d35,0xbcc43d6d,0x3d80,0x3cc43d6d,0x3d353d35,0x3d6d3cc4,0x3d800000,0x3d6dbcc4,0x3d35bd35,0x3cc4bd6d,
0xbd80,0xbcc4bd6d,0xbd35bd35,0xbd6dbcc4,0xbd800000,0xbd6d3cc4,0xbd353d35,0xbcc43d6d,0x3d80,0x3cc43d6d,0x3d353d35,0x3d6d3cc4,0x3d800000,0x3d6dbcc4,0x3d35bd35,0x3cc4bd6d,
0xbd353d35,0xbd0e3d55,0xbcc43d6d,0xbc483d7b,0xbd800000,0xbd7b3c48,0xbd6d3cc4,0xbd553d0e,0xbd35bd35,0xbd55bd0e,0xbd6dbcc4,0xbd7bbc48,0xbd80,0xbc48bd7b,0xbcc4bd6d,0xbd0ebd55,
0x3d35bd35,0x3d0ebd55,0x3cc4bd6d,0x3c48bd7b,0x3d800000,0x3d7bbc48,0x3d6dbcc4,0x3d55bd0e,0x3d353d35,0x3d553d0e,0x3d6d3cc4,0x3d7b3c48,0x3d80,0x3c483d7b,0x3cc43d6d,0x3d0e3d55,
0xbd800000,0x80003d80,0x3d800000,0x8000bd80,0xbd800000,0x80003d80,0x3d800000,0x8000bd80,0xbd800000,0x80003d80,0x3d800000,0x8000bd80,0xbd800000,0x80003d80,0x3d800000,0x8000bd80,
0xbd800000,0x80003d80,0x3d800000,0x8000bd80,0xbd800000,0x80003d80,0x3d800000,0x8000bd80,0xbd800000,0x80003d80,0x3d800000,0x8000bd80,0xbd800000,0x80003d80,0x3d800000,0x8000bd80,
0xbd35bd35,0xbd553d0e,0x3cc43d6d,0x3d7bbc48,0xbd800000,0xbc483d7b,0x3d6d3cc4,0x3d0ebd55,0x3d35bd35,0xbd0ebd55,0xbd6d3cc4,0x3c483d7b,0x8000bd80,0xbd7bbc48,0xbcc43d6d,0x3d553d0e,
0x3d353d35,0x3d55bd0e,0xbcc4bd6d,0xbd7b3c48,0x3d800000,0x3c48bd7b,0xbd6dbcc4,0xbd0e3d55,0xbd353d35,0x3d0e3d55,0x3d6dbcc4,0xbc48bd7b,0x80003d80,0x3d7b3c48,0x3cc4bd6d,0xbd55bd0e,
0x3d800000,0x3cc4bd6d,0xbd35bd35,0xbd6d3cc4,0x80003d80,0x3d6d3cc4,0x3d35bd35,0xbcc4bd6d,0xbd800000,0xbcc43d6d,0x3d353d35,0x3d6dbcc4,0x8000bd80,0xbd6dbcc4,0xbd353d35,0x3cc43d6d,
0x3d800000,0x3cc4bd6d,0xbd35bd35,0xbd6d3cc4,0x80003d80,0x3d6d3cc4,0x3d35bd35,0xbcc4bd6d,0xbd800000,0xbcc43d6d,0x3d353d35,0x3d6dbcc4,0x8000bd80,0xbd6dbcc4,0xbd353d35,0x3cc43d6d,
0xbd35bd35,0xbd7b3c48,0xbcc43d6d,0x3d0e3d55,0x80003d80,0x3d553d0e,0x3d6dbcc4,0x3c48bd7b,0x3d35bd35,0xbc48bd7b,0xbd6dbcc4,0xbd553d0e,0xbd800000,0xbd0e3d55,0x3cc43d6d,0x3d7b3c48,
0x3d353d35,0x3d7bbc48,0x3cc4bd6d,0xbd0ebd55,0x8000bd80,0xbd55bd0e,0xbd6d3cc4,0xbc483d7b,0xbd353d35,0x3c483d7b,0x3d6d3cc4,0x3d55bd0e,0x3d800000,0x3d0ebd55,0xbcc4bd6d,0xbd7bbc48,
0xbd800000,0xbd353d35,0x80003d80,0x3d353d35,0x3d800000,0x3d35bd35,0x8000bd80,0xbd35bd35,0xbd800000,0xbd353d35,0x80003d80,0x3d353d35,0x3d800000,0x3d35bd35,0x8000bd80,0xbd35bd35,
0xbd800000,0xbd353d35,0x80003d80,0x3d353d35,0x3d800000,0x3d35bd35,0x8000bd80,0xbd35bd35,0xbd800000,0xbd353d35,0x80003d80,0x3d353d35,0x3d800000,0x3d35bd35,0x8000bd80,0xbd35bd35,
0xbd35bd35,0xbd7bbc48,0xbd6d3cc4,0xbd0e3d55,0x3d800000,0x3d55bd0e,0x3cc4bd6d,0xbc48bd7b,0x3d35bd35,0x3c48bd7b,0xbcc4bd6d,0xbd55bd0e,0x80003d80,0x3d0e3d55,0x3d6d3cc4,0x3d7bbc48,
0x3d353d35,0x3d7b3c48,0x3d6dbcc4,0x3d0ebd55,0xbd800000,0xbd553d0e,0xbcc43d6d,0x3c483d7b,0xbd353d35,0xbc483d7b,0x3cc43d6d,0x3d553d0e,0x8000bd80,0xbd0ebd55,0xbd6dbcc4,0xbd7b3c48,
0x3d800000,0x3d6dbcc4,0x3d35bd35,0x3cc4bd6d,0x8000bd80,0xbcc4bd6d,0xbd35bd35,0xbd6dbcc4,0xbd800000,0xbd6d3cc4,0xbd353d35,0xbcc43d6d,0x80003d80,0x3cc43d6d,0x3d353d35,0x3d6d3cc4,
0x3d800000,0x3d6dbcc4,0x3d35bd35,0x3cc4bd6d,0x8000bd80,0xbcc4bd6d,0xbd35bd35,0xbd6dbcc4,0xbd800000,0xbd6d3cc4,0xbd353d35,0xbcc43d6d,0x80003d80,0x3cc43d6d,0x3d353d35,0x3d6d3cc4,
0xbd35bd35,0xbd55bd0e,0xbd6dbcc4,0xbd7bbc48,0x8000bd80,0xbc48bd7b,0xbcc4bd6d,0xbd0ebd55,0x3d35bd35,0x3d0ebd55,0x3cc4bd6d,0x3c48bd7b,0x3d800000,0x3d7bbc48,0x3d6dbcc4,0x3d55bd0e,
0x3d353d35,0x3d553d0e,0x3d6d3cc4,0x3d7b3c48,0x80003d80,0x3c483d7b,0x3cc43d6d,0x3d0e3d55,0xbd353d35,0xbd0e3d55,0xbcc43d6d,0xbc483d7b,0xbd800000,0xbd7b3c48,0xbd6d3cc4,0xbd553d0e,
0x3d80,0xbb493d80,0xbbc93d7f,0xbc163d7d,0xbc483d7b,0xbc793d78,0xbc953d75,0xbcac3d71,0xbcc43d6d,0xbcdb3d67,0xbcf13d62,0xbd043d5c,0xbd0e3d55,0xbd183d4e,0xbd223d46,0xbd2c3d3e,
0xbd353d35,0xbd3e3d2c,0xbd463d22,0xbd4e3d18,0xbd553d0e,0xbd5c3d04,0xbd623cf1,0xbd673cdb,0xbd6d3cc4,0xbd713cac,0xbd753c95,0xbd783c79,0xbd7b3c48,0xbd7d3c16,0xbd7f3bc9,0xbd803b49,
0xbd553d0e,0xbd713cac,0xbd7f3bc9,0xbd7dbc16,0x3d80,0xbc793d78,0xbcf13d62,0xbd2c3d3e,0xbc48bd7b,0x3b49bd80,0x3c95bd75,0x3d04bd5c,0xbd6dbcc4,0xbd4ebd18,0xbd22bd46,0xbcdbbd67,
0x3d7b3c48,0x3d673cdb,0x3d463d22,0x3d183d4e,0x3d35bd35,0x3d5cbd04,0x3d75bc95,0x3d80bb49,0xbd0e3d55,0xbd3e3d2c,0xbd623cf1,0xbd783c79,0x3cc43d6d,0x3c163d7d,0xbbc93d7f,0xbcac3d71,
0x3cc4bd6d,0x3d3ebd2c,0x3d75bc95,0x3d7d3c16,0x3d553d0e,0x3d043d5c,0x3bc93d7f,0xbcac3d71,0x3d80,0xbcdb3d67,0xbd463d22,0xbd783c79,0xbd7bbc48,0xbd4ebd18,0xbcf1bd62,0xbb49bd80,
0x3d6dbcc4,0x3d803b49,0x3d623cf1,0x3d183d4e,0x3c483d7b,0xbc793d78,0xbd223d46,0xbd673cdb,0xbd353d35,0xbd713cac,0xbd7fbbc9,0xbd5cbd04,0xbd0ebd55,0xbc16bd7d,0x3c95bd75,0x3d2cbd3e,
0xbd7b3c48,0xbd67bcdb,0xbcf1bd62,0x3c16bd7d,0x3d6d3cc4,0x3d043d5c,0xbbc93d7f,0xbd2c3d3e,0xbd0ebd55,0x3b49bd80,0x3d22bd46,0x3d78bc79,0x3d80,0xbd183d4e,0xbd753c95,0xbd71bcac,
0x3d553d0e,0x3cac3d71,0xbc953d75,0xbd4e3d18,0xbcc4bd6d,0x3c79bd78,0x3d46bd22,0x3d80bb49,0xbc483d7b,0xbd3e3d2c,0xbd7f3bc9,0xbd5cbd04,0x3d35bd35,0x3d7dbc16,0x3d623cf1,0x3cdb3d67,
0xbd353d35,0xbd80bb49,0xbd22bd46,0x3c16bd7d,0x3d55bd0e,0x3d783c79,0x3cf13d62,0xbcac3d71,0xbd6d3cc4,0xbd67bcdb,0xbc95bd75,0x3d04bd5c,0x3d7bbc48,0x3d4e3d18,0x3bc93d7f,0xbd2c3d3e,
0x3d80,0xbd3e3d2c,0xbd7fbbc9,0xbd18bd4e,0x3c48bd7b,0x3d5cbd04,0x3d753c95,0x3cdb3d67,0xbcc43d6d,0xbd713cac,0xbd62bcf1,0xbc79bd78,0x3d0ebd55,0x3d7dbc16,0x3d463d22,0x3b493d80,
0xbd7bbc48,0xbcacbd71,0x3d22bd46,0x3d7d3c16,0x3d35bd35,0x3d783c79,0x3c953d75,0xbd2c3d3e,0x3d0ebd55,0x3d803b49,0x3cf13d62,0xbd043d5c,0x3cc43d6d,0xbd183d4e,0xbd7fbbc9,0xbcdbbd67,
0x3d55bd0e,0x3d673cdb,0x3bc93d7f,0xbd4e3d18,0x3d80,0xbd5c3d04,0xbd62bcf1,0xbb49bd80,0x3c483d7b,0xbd3e3d2c,0xbd75bc95,0xbc79bd78,0xbd6dbcc4,0xbc16bd7d,0x3d46bd22,0x3d713cac,
0x3d6dbcc4,0x3d2c3d3e,0xbcf13d62,0xbd7dbc16,0xbc48bd7b,0x3d5cbd04,0x3d463d22,0xbcac3d71,0xbd353d35,0xbd67bcdb,0x3bc9bd7f,0x3d78bc79,0x3d0e3d55,0xbd183d4e,0xbd75bc95,0xbb49bd80,
0x3cc4bd6d,0x3d803b49,0x3c953d75,0xbd4e3d18,0xbd55bd0e,0x3c79bd78,0x3d7fbbc9,0x3cdb3d67,0x3d80,0xbd713cac,0xbd22bd46,0x3d04bd5c,0x3d7b3c48,0x3c163d7d,0xbd623cf1,0xbd3ebd2c,
0xbd55bd0e,0x3cdbbd67,0x3d753c95,0xbc163d7d,0xbcc4bd6d,0x3d5cbd04,0x3d223d46,0xbd2c3d3e,0x3c48bd7b,0x3d803b49,0x3bc93d7f,0xbd783c79,0x3d35bd35,0x3d4e3d18,0xbcf13d62,0xbd71bcac,
0x3d7bbc48,0x3cac3d71,0xbd623cf1,0xbd18bd4e,0x3d6d3cc4,0xbc793d78,0xbd7fbbc9,0xbb49bd80,0x3d0e3d55,0xbd3e3d2c,0xbd46bd22,0x3d04bd5c,0x3d80,0xbd7d3c16,0xbc95bd75,0x3d67bcdb,
0xbd800000,0xbd80bb49,0xbd7fbbc9,0xbd7dbc16,0xbd7bbc48,0xbd78bc79,0xbd75bc95,0xbd71bcac,0xbd6dbcc4,0xbd67bcdb,0xbd62bcf1,0xbd5cbd04,0xbd55bd0e,0xbd4ebd18,0xbd46bd22,0xbd3ebd2c,
0xbd35bd35,0xbd2cbd3e,0xbd22bd46,0xbd18bd4e,0xbd0ebd55,0xbd04bd5c,0xbcf1bd62,0xbcdbbd67,0xbcc4bd6d,0xbcacbd71,0xbc95bd75,0xbc79bd78,0xbc48bd7b,0xbc16bd7d,0xbbc9bd7f,0xbb49bd80,
0xbd0ebd55,0xbcacbd71,0xbbc9bd7f,0x3c16bd7d,0xbd800000,0xbd78bc79,0xbd62bcf1,0xbd3ebd2c,0x3d7bbc48,0x3d803b49,0x3d753c95,0x3d5c3d04,0x3cc4bd6d,0x3d18bd4e,0x3d46bd22,0x3d67bcdb,
0xbc483d7b,0xbcdb3d67,0xbd223d46,0xbd4e3d18,0x3d353d35,0x3d043d5c,0x3c953d75,0x3b493d80,0xbd55bd0e,0xbd2cbd3e,0xbcf1bd62,0xbc79bd78,0xbd6d3cc4,0xbd7d3c16,0xbd7fbbc9,0xbd71bcac,
0x3d6d3cc4,0x3d2c3d3e,0x3c953d75,0xbc163d7d,0xbd0e3d55,0xbd5c3d04,0xbd7f3bc9,0xbd71bcac,0xbd800000,0xbd67bcdb,0xbd22bd46,0xbc79bd78,0x3c48bd7b,0x3d18bd4e,0x3d62bcf1,0x3d80bb49,
0x3cc43d6d,0xbb493d80,0xbcf13d62,0xbd4e3d18,0xbd7b3c48,0xbd78bc79,0xbd46bd22,0xbcdbbd67,0xbd35bd35,0xbcacbd71,0x3bc9bd7f,0x3d04bd5c,0x3d55bd0e,0x3d7dbc16,0x3d753c95,0x3d3e3d2c,
0xbc48bd7b,0x3cdbbd67,0x3d62bcf1,0x3d7d3c16,0xbcc43d6d,0xbd5c3d04,0xbd7fbbc9,0xbd3ebd2c,0x3d55bd0e,0x3d803b49,0x3d463d22,0x3c793d78,0xbd800000,0xbd4ebd18,0xbc95bd75,0x3cacbd71,
0xbd0e3d55,0xbd713cac,0xbd75bc95,0xbd18bd4e,0x3d6dbcc4,0x3d783c79,0x3d223d46,0x3b493d80,0xbd7bbc48,0xbd2cbd3e,0xbbc9bd7f,0x3d04bd5c,0x3d353d35,0x3c163d7d,0xbcf13d62,0xbd673cdb,
0xbd35bd35,0x3b49bd80,0x3d46bd22,0x3d7d3c16,0x3d0e3d55,0xbc793d78,0xbd623cf1,0xbd71bcac,0xbcc4bd6d,0x3cdbbd67,0x3d75bc95,0x3d5c3d04,0x3c483d7b,0xbd183d4e,0xbd7f3bc9,0xbd3ebd2c,
0xbd800000,0xbd2cbd3e,0x3bc9bd7f,0x3d4ebd18,0x3d7b3c48,0x3d043d5c,0xbc953d75,0xbd673cdb,0xbd6dbcc4,0xbcacbd71,0x3cf1bd62,0x3d78bc79,0x3d553d0e,0x3c163d7d,0xbd223d46,0xbd803b49,
0x3c48bd7b,0x3d71bcac,0x3d463d22,0xbc163d7d,0x3d353d35,0xbc793d78,0xbd753c95,0xbd3ebd2c,0x3d553d0e,0xbb493d80,0xbd623cf1,0xbd5cbd04,0xbd6d3cc4,0xbd4ebd18,0x3bc9bd7f,0x3d67bcdb,
0x3d0e3d55,0xbcdb3d67,0xbd7f3bc9,0xbd18bd4e,0xbd800000,0xbd04bd5c,0x3cf1bd62,0x3d80bb49,0xbd7b3c48,0xbd2cbd3e,0x3c95bd75,0x3d78bc79,0x3cc4bd6d,0x3d7dbc16,0x3d223d46,0xbcac3d71,
0x3cc43d6d,0xbd3e3d2c,0xbd62bcf1,0x3c16bd7d,0x3d7bbc48,0x3d043d5c,0xbd223d46,0xbd71bcac,0xbd35bd35,0x3cdbbd67,0x3d7f3bc9,0x3c793d78,0xbd553d0e,0xbd4ebd18,0x3c95bd75,0x3d80bb49,
0x3d6d3cc4,0xbb493d80,0xbd753c95,0xbd18bd4e,0x3d0ebd55,0x3d783c79,0x3bc93d7f,0xbd673cdb,0xbd800000,0xbcacbd71,0x3d46bd22,0x3d5c3d04,0xbc483d7b,0xbd7d3c16,0xbcf1bd62,0x3d2cbd3e,
0x3d0ebd55,0x3d673cdb,0xbc953d75,0xbd7dbc16,0x3d6dbcc4,0x3d043d5c,0xbd463d22,0xbd3ebd2c,0x3d7b3c48,0xbb493d80,0xbd7f3bc9,0xbc79bd78,0x3d353d35,0xbd183d4e,0xbd62bcf1,0x3cacbd71,
0x3c483d7b,0xbd713cac,0xbcf1bd62,0x3d4ebd18,0xbcc43d6d,0xbd78bc79,0x3bc9bd7f,0x3d80bb49,0xbd553d0e,0xbd2cbd3e,0x3d22bd46,0x3d5c3d04,0xbd800000,0xbc16bd7d,0x3d75bc95,0x3cdb3d67,
0x3d80,0xbd80bb49,0x3bc9bd7f,0x3d7d3c16,0xbc483d7b,0xbd78bc79,0x3c95bd75,0x3d713cac,0xbcc43d6d,0xbd67bcdb,0x3cf1bd62,0x3d5c3d04,0xbd0e3d55,0xbd4ebd18,0x3d22bd46,0x3d3e3d2c,
0xbd353d35,0xbd2cbd3e,0x3d46bd22,0x3d183d4e,0xbd553d0e,0xbd04bd5c,0x3d62bcf1,0x3cdb3d67,0xbd6d3cc4,0xbcacbd71,0x3d75bc95,0x3c793d78,0xbd7b3c48,0xbc16bd7d,0x3d7fbbc9,0x3b493d80,
0xbd553d0e,0xbcacbd71,0x3d7fbbc9,0xbc163d7d,0x3d80,0xbd78bc79,0x3cf1bd62,0x3d3e3d2c,0xbc48bd7b,0x3d803b49,0xbc953d75,0xbd5cbd04,0xbd6dbcc4,0x3d18bd4e,0x3d223d46,0xbd673cdb,
0x3d7b3c48,0xbcdb3d67,0xbd46bd22,0x3d4ebd18,0x3d35bd35,0x3d043d5c,0xbd753c95,0xbb49bd80,0xbd0e3d55,0xbd2cbd3e,0x3d62bcf1,0x3c793d78,0x3cc43d6d,0xbd7d3c16,0x3bc9bd7f,0x3d713cac,
0x3cc4bd6d,0x3d2c3d3e,0xbd753c95,0x3c16bd7d,0x3d553d0e,0xbd5c3d04,0xbbc9bd7f,0x3d713cac,0x3d80,0xbd67bcdb,0x3d46bd22,0x3c793d78,0xbd7bbc48,0x3d18bd4e,0x3cf13d62,0xbd803b49,
0x3d6dbcc4,0xbb493d80,0xbd62bcf1,0x3d4ebd18,0x3c483d7b,0xbd78bc79,0x3d22bd46,0x3cdb3d67,0xbd353d35,0xbcacbd71,0x3d7f3bc9,0xbd043d5c,0xbd0ebd55,0x3d7dbc16,0xbc953d75,0xbd3ebd2c,
0xbd7b3c48,0x3cdbbd67,0x3cf13d62,0xbd7dbc16,0x3d6d3cc4,0xbd5c3d04,0x3bc9bd7f,0x3d3e3d2c,0xbd0ebd55,0x3d803b49,0xbd223d46,0xbc79bd78,0x3d80,0xbd4ebd18,0x3d75bc95,0xbcac3d71,
0x3d553d0e,0xbd713cac,0x3c95bd75,0x3d183d4e,0xbcc4bd6d,0x3d783c79,0xbd463d22,0xbb49bd80,0xbc483d7b,0xbd2cbd3e,0x3d7fbbc9,0xbd043d5c,0x3d35bd35,0x3c163d7d,0xbd62bcf1,0x3d67bcdb,
0xbd353d35,0x3b49bd80,0x3d223d46,0xbd7dbc16,0x3d55bd0e,0xbc793d78,0xbcf1bd62,0x3d713cac,0xbd6d3cc4,0x3cdbbd67,0x3c953d75,0xbd5cbd04,0x3d7bbc48,0xbd183d4e,0xbbc9bd7f,0x3d3e3d2c,
0x3d80,0xbd2cbd3e,0x3d7f3bc9,0xbd4e3d18,0x3c48bd7b,0x3d043d5c,0xbd75bc95,0x3d67bcdb,0xbcc43d6d,0xbcacbd71,0x3d623cf1,0xbd783c79,0x3d0ebd55,0x3c163d7d,0xbd46bd22,0x3d80bb49,
0xbd7bbc48,0x3d71bcac,0xbd223d46,0x3c16bd7d,0x3d35bd35,0xbc793d78,0xbc95bd75,0x3d3e3d2c,0x3d0ebd55,0xbb493d80,0xbcf1bd62,0x3d5c3d04,0x3cc43d6d,0xbd4ebd18,0x3d7f3bc9,0xbd673cdb,
0x3d55bd0e,0xbcdb3d67,0xbbc9bd7f,0x3d183d4e,0x3d80,0xbd04bd5c,0x3d623cf1,0xbd803b49,0x3c483d7b,0xbd2cbd3e,0x3d753c95,0xbd783c79,0xbd6dbcc4,0x3d7dbc16,0xbd463d22,0x3cacbd71,
0x3d6dbcc4,0xbd3e3d2c,0x3cf1bd62,0xbc163d7d,0xbc48bd7b,0x3d043d5c,0xbd46bd22,0x3d713cac,0xbd353d35,0x3cdbbd67,0xbbc93d7f,0xbc79bd78,0x3d0e3d55,0xbd4ebd18,0x3d753c95,0xbd803b49,
0x3cc4bd6d,0xbb493d80,0xbc95bd75,0x3d183d4e,0xbd55bd0e,0x3d783c79,0xbd7f3bc9,0x3d67bcdb,0x3d80,0xbcacbd71,0x3d223d46,0xbd5cbd04,0x3d7b3c48,0xbd7d3c16,0x3d62bcf1,0xbd2c3d3e,
0xbd55bd0e,0x3d673cdb,0xbd75bc95,0x3d7d3c16,0xbcc4bd6d,0x3d043d5c,0xbd22bd46,0x3d3e3d2c,0x3c48bd7b,0xbb493d80,0xbbc9bd7f,0x3c793d78,0x3d35bd35,0xbd183d4e,0x3cf1bd62,0xbcac3d71,
0x3d7bbc48,0xbd713cac,0x3d62bcf1,0xbd4e3d18,0x3d6d3cc4,0xbd78bc79,0x3d7f3bc9,0xbd803b49,0x3d0e3d55,0xbd2cbd3e,0x3d463d22,0xbd5cbd04,0x3d80,0xbc16bd7d,0x3c953d75,0xbcdbbd67,
0xbd800000,0x3b49bd80,0x3d7f3bc9,0xbc163d7d,0xbd7bbc48,0x3c79bd78,0x3d753c95,0xbcac3d71,0xbd6dbcc4,0x3cdbbd67,0x3d623cf1,0xbd043d5c,0xbd55bd0e,0x3d18bd4e,0x3d463d22,0xbd2c3d3e,
0xbd35bd35,0x3d3ebd2c,0x3d223d46,0xbd4e3d18,0xbd0ebd55,0x3d5cbd04,0x3cf13d62,0xbd673cdb,0xbcc4bd6d,0x3d71bcac,0x3c953d75,0xbd783c79,0xbc48bd7b,0x3d7dbc16,0x3bc93d7f,0xbd803b49,
0xbd0ebd55,0x3d71bcac,0x3bc93d7f,0xbd7dbc16,0xbd800000,0x3c79bd78,0x3d623cf1,0xbd2c3d3e,0x3d7bbc48,0xbb493d80,0xbd75bc95,0x3d04bd5c,0x3cc4bd6d,0x3d4e3d18,0xbd463d22,0xbcdbbd67,
0xbc483d7b,0xbd67bcdb,0x3d22bd46,0x3d183d4e,0x3d353d35,0xbd5c3d04,0xbc95bd75,0x3d80bb49,0xbd55bd0e,0x3d3ebd2c,0x3cf13d62,0xbd783c79,0xbd6d3cc4,0xbc16bd7d,0x3d7f3bc9,0xbcac3d71,
0x3d6d3cc4,0xbd3e3d2c,0xbc95bd75,0x3d7d3c16,0xbd0e3d55,0xbd04bd5c,0x3d7fbbc9,0xbcac3d71,0xbd800000,0x3cdbbd67,0x3d223d46,0xbd783c79,0x3c48bd7b,0x3d4e3d18,0xbd623cf1,0xbb49bd80,
0x3cc43d6d,0xbd80bb49,0x3cf1bd62,0x3d183d4e,0xbd7b3c48,0x3c79bd78,0x3d463d22,0xbd673cdb,0xbd35bd35,0x3d71bcac,0xbbc93d7f,0xbd5cbd04,0x3d55bd0e,0x3c163d7d,0xbd75bc95,0x3d2cbd3e,
0xbc48bd7b,0x3d673cdb,0xbd623cf1,0x3c16bd7d,0xbcc43d6d,0xbd04bd5c,0x3d7f3bc9,0xbd2c3d3e,0x3d55bd0e,0xbb493d80,0xbd46bd22,0x3d78bc79,0xbd800000,0x3d18bd4e,0x3c953d75,0xbd71bcac,
0xbd0e3d55,0xbcacbd71,0x3d753c95,0xbd4e3d18,0x3d6dbcc4,0xbc793d78,0xbd22bd46,0x3d80bb49,0xbd7bbc48,0x3d3ebd2c,0x3bc93d7f,0xbd5cbd04,0x3d353d35,0xbd7d3c16,0x3cf1bd62,0x3cdb3d67,
0xbd35bd35,0x3d803b49,0xbd463d22,0x3c16bd7d,0x3d0e3d55,0xbd78bc79,0x3d62bcf1,0xbcac3d71,0xbcc4bd6d,0x3d673cdb,0xbd753c95,0x3d04bd5c,0x3c483d7b,0xbd4ebd18,0x3d7fbbc9,0xbd2c3d3e,
0xbd800000,0x3d3ebd2c,0xbbc93d7f,0xbd18bd4e,0x3d7b3c48,0xbd5c3d04,0x3c95bd75,0x3cdb3d67,0xbd6dbcc4,0x3d71bcac,0xbcf13d62,0xbc79bd78,0x3d553d0e,0xbd7d3c16,0x3d22bd46,0x3b493d80,
0x3c48bd7b,0x3cac3d71,0xbd46bd22,0x3d7d3c16,0x3d353d35,0xbd78bc79,0x3d75bc95,0xbd2c3d3e,0x3d553d0e,0xbd80bb49,0x3d62bcf1,0xbd043d5c,0xbd6d3cc4,0x3d18bd4e,0xbbc93d7f,0xbcdbbd67,
0x3d0e3d55,0xbd67bcdb,0x3d7fbbc9,0xbd4e3d18,0xbd800000,0x3d5cbd04,0xbcf13d62,0xbb49bd80,0xbd7b3c48,0x3d3ebd2c,0xbc953d75,0xbc79bd78,0x3cc4bd6d,0x3c163d7d,0xbd22bd46,0x3d713cac,
0x3cc43d6d,0xbd2cbd3e,0x3d623cf1,0xbd7dbc16,0x3d7bbc48,0xbd5c3d04,0x3d22bd46,0xbcac3d71,0xbd35bd35,0x3d673cdb,0xbd7fbbc9,0x3d78bc79,0xbd553d0e,0x3d18bd4e,0xbc953d75,0xbb49bd80,
0x3d6d3cc4,0xbd80bb49,0x3d75bc95,0xbd4e3d18,0x3d0ebd55,0xbc793d78,0xbbc9bd7f,0x3cdb3d67,0xbd800000,0x3d71bcac,0xbd463d22,0x3d04bd5c,0xbc483d7b,0xbc16bd7d,0x3cf13d62,0xbd3ebd2c,
0x3d0ebd55,0xbcdb3d67,0x3c95bd75,0xbc163d7d,0x3d6dbcc4,0xbd5c3d04,0x3d46bd22,0xbd2c3d3e,0x3d7b3c48,0xbd80bb49,0x3d7fbbc9,0xbd783c79,0x3d353d35,0xbd4ebd18,0x3d623cf1,0xbd71bcac,
0x3c483d7b,0xbcacbd71,0x3cf13d62,0xbd18bd4e,0xbcc43d6d,0x3c79bd78,0xbbc93d7f,0xbb49bd80,0xbd553d0e,0x3d3ebd2c,0xbd223d46,0x3d04bd5c,0xbd800000,0x3d7dbc16,0xbd753c95,0x3d67bcdb,
0x3d80,0x3b49bd80,0xbbc93d7f,0x3c16bd7d,0xbc483d7b,0x3c79bd78,0xbc953d75,0x3cacbd71,0xbcc43d6d,0x3cdbbd67,0xbcf13d62,0x3d04bd5c,0xbd0e3d55,0x3d18bd4e,0xbd223d46,0x3d2cbd3e,
0xbd353d35,0x3d3ebd2c,0xbd463d22,0x3d4ebd18,0xbd553d0e,0x3d5cbd04,0xbd623cf1,0x3d67bcdb,0xbd6d3cc4,0x3d71bcac,0xbd753c95,0x3d78bc79,0xbd7b3c48,0x3d7dbc16,0xbd7f3bc9,0x3d80bb49,
0xbd553d0e,0x3d71bcac,0xbd7f3bc9,0x3d7d3c16,0x3d80,0x3c79bd78,0xbcf13d62,0x3d2cbd3e,0xbc48bd7b,0xbb493d80,0x3c95bd75,0xbd043d5c,0xbd6dbcc4,0x3d4e3d18,0xbd22bd46,0x3cdb3d67,
0x3d7b3c48,0xbd67bcdb,0x3d463d22,0xbd18bd4e,0x3d35bd35,0xbd5c3d04,0x3d75bc95,0xbd803b49,0xbd0e3d55,0x3d3ebd2c,0xbd623cf1,0x3d78bc79,0x3cc43d6d,0xbc16bd7d,0xbbc93d7f,0x3cacbd71,
0x3cc4bd6d,0xbd3e3d2c,0x3d75bc95,0xbd7dbc16,0x3d553d0e,0xbd04bd5c,0x3bc93d7f,0x3cacbd71,0x3d80,0x3cdbbd67,0xbd463d22,0x3d78bc79,0xbd7bbc48,0x3d4e3d18,0xbcf1bd62,0x3b493d80,
0x3d6dbcc4,0xbd80bb49,0x3d623cf1,0xbd18bd4e,0x3c483d7b,0x3c79bd78,0xbd223d46,0x3d67bcdb,0xbd353d35,0x3d71bcac,0xbd7fbbc9,0x3d5c3d04,0xbd0ebd55,0x3c163d7d,0x3c95bd75,0xbd2c3d3e,
0xbd7b3c48,0x3d673cdb,0xbcf1bd62,0xbc163d7d,0x3d6d3cc4,0xbd04bd5c,0xbbc93d7f,0x3d2cbd3e,0xbd0ebd55,0xbb493d80,0x3d22bd46,0xbd783c79,0x3d80,0x3d18bd4e,0xbd753c95,0x3d713cac,
0x3d553d0e,0xbcacbd71,0xbc953d75,0x3d4ebd18,0xbcc4bd6d,0xbc793d78,0x3d46bd22,0xbd803b49,0xbc483d7b,0x3d3ebd2c,0xbd7f3bc9,0x3d5c3d04,0x3d35bd35,0xbd7d3c16,0x3d623cf1,0xbcdbbd67,
0xbd353d35,0x3d803b49,0xbd22bd46,0xbc163d7d,0x3d55bd0e,0xbd78bc79,0x3cf13d62,0x3cacbd71,0xbd6d3cc4,0x3d673cdb,0xbc95bd75,0xbd043d5c,0x3d7bbc48,0xbd4ebd18,0x3bc93d7f,0x3d2cbd3e,
0x3d80,0x3d3ebd2c,0xbd7fbbc9,0x3d183d4e,0x3c48bd7b,0xbd5c3d04,0x3d753c95,0xbcdbbd67,0xbcc43d6d,0x3d71bcac,0xbd62bcf1,0x3c793d78,0x3d0ebd55,0xbd7d3c16,0x3d463d22,0xbb49bd80,
0xbd7bbc48,0x3cac3d71,0x3d22bd46,0xbd7dbc16,0x3d35bd35,0xbd78bc79,0x3c953d75,0x3d2cbd3e,0x3d0ebd55,0xbd80bb49,0x3cf13d62,0x3d04bd5c,0x3cc43d6d,0x3d18bd4e,0xbd7fbbc9,0x3cdb3d67,
0x3d55bd0e,0xbd67bcdb,0x3bc93d7f,0x3d4ebd18,0x3d80,0x3d5cbd04,0xbd62bcf1,0x3b493d80,0x3c483d7b,0x3d3ebd2c,0xbd75bc95,0x3c793d78,0xbd6dbcc4,0x3c163d7d,0x3d46bd22,0xbd71bcac,
0x3d6dbcc4,0xbd2cbd3e,0xbcf13d62,0x3d7d3c16,0xbc48bd7b,0xbd5c3d04,0x3d463d22,0x3cacbd71,0xbd353d35,0x3d673cdb,0x3bc9bd7f,0xbd783c79,0x3d0e3d55,0x3d18bd4e,0xbd75bc95,0x3b493d80,
0x3cc4bd6d,0xbd80bb49,0x3c953d75,0x3d4ebd18,0xbd55bd0e,0xbc793d78,0x3d7fbbc9,0xbcdbbd67,0x3d80,0x3d71bcac,0xbd22bd46,0xbd043d5c,0x3d7b3c48,0xbc16bd7d,0xbd623cf1,0x3d3e3d2c,
0xbd55bd0e,0xbcdb3d67,0x3d753c95,0x3c16bd7d,0xbcc4bd6d,0xbd5c3d04,0x3d223d46,0x3d2cbd3e,0x3c48bd7b,0xbd80bb49,0x3bc93d7f,0x3d78bc79,0x3d35bd35,0xbd4ebd18,0xbcf13d62,0x3d713cac,
0x3d7bbc48,0xbcacbd71,0xbd623cf1,0x3d183d4e,0x3d6d3cc4,0x3c79bd78,0xbd7fbbc9,0x3b493d80,0x3d0e3d55,0x3d3ebd2c,0xbd46bd22,0xbd043d5c,0x3d80,0x3d7dbc16,0xbc95bd75,0xbd673cdb,
0xbd800000,0x3d803b49,0xbd7fbbc9,0x3d7d3c16,0xbd7bbc48,0x3d783c79,0xbd75bc95,0x3d713cac,0xbd6dbcc4,0x3d673cdb,0xbd62bcf1,0x3d5c3d04,0xbd55bd0e,0x3d4e3d18,0xbd46bd22,0x3d3e3d2c,
0xbd35bd35,0x3d2c3d3e,0xbd22bd46,0x3d183d4e,0xbd0ebd55,0x3d043d5c,0xbcf1bd62,0x3cdb3d67,0xbcc4bd6d,0x3cac3d71,0xbc95bd75,0x3c793d78,0xbc48bd7b,0x3c163d7d,0xbbc9bd7f,0x3b493d80,
0xbd0ebd55,0x3cac3d71,0xbbc9bd7f,0xbc163d7d,0xbd800000,0x3d783c79,0xbd62bcf1,0x3d3e3d2c,0x3d7bbc48,0xbd80bb49,0x3d753c95,0xbd5cbd04,0x3cc4bd6d,0xbd183d4e,0x3d46bd22,0xbd673cdb,
0xbc483d7b,0x3cdbbd67,0xbd223d46,0x3d4ebd18,0x3d353d35,0xbd04bd5c,0x3c953d75,0xbb49bd80,0xbd55bd0e,0x3d2c3d3e,0xbcf1bd62,0x3c793d78,0xbd6d3cc4,0x3d7dbc16,0xbd7fbbc9,0x3d713cac,
0x3d6d3cc4,0xbd2cbd3e,0x3c953d75,0x3c16bd7d,0xbd0e3d55,0x3d5cbd04,0xbd7f3bc9,0x3d713cac,0xbd800000,0x3d673cdb,0xbd22bd46,0x3c793d78,0x3c48bd7b,0xbd183d4e,0x3d62bcf1,0xbd803b49,
0x3cc43d6d,0x3b49bd80,0xbcf13d62,0x3d4ebd18,0xbd7b3c48,0x3d783c79,0xbd46bd22,0x3cdb3d67,0xbd35bd35,0x3cac3d71,0x3bc9bd7f,0xbd043d5c,0x3d55bd0e,0xbd7d3c16,0x3d753c95,0xbd3ebd2c,
0xbc48bd7b,0xbcdb3d67,0x3d62bcf1,0xbd7dbc16,0xbcc43d6d,0x3d5cbd04,0xbd7fbbc9,0x3d3e3d2c,0x3d55bd0e,0xbd80bb49,0x3d463d22,0xbc79bd78,0xbd800000,0x3d4e3d18,0xbc95bd75,0xbcac3d71,
0xbd0e3d55,0x3d71bcac,0xbd75bc95,0x3d183d4e,0x3d6dbcc4,0xbd78bc79,0x3d223d46,0xbb49bd80,0xbd7bbc48,0x3d2c3d3e,0xbbc9bd7f,0xbd043d5c,0x3d353d35,0xbc16bd7d,0xbcf13d62,0x3d67bcdb,
0xbd35bd35,0xbb493d80,0x3d46bd22,0xbd7dbc16,0x3d0e3d55,0x3c79bd78,0xbd623cf1,0x3d713cac,0xbcc4bd6d,0xbcdb3d67,0x3d75bc95,0xbd5cbd04,0x3c483d7b,0x3d18bd4e,0xbd7f3bc9,0x3d3e3d2c,
0xbd800000,0x3d2c3d3e,0x3bc9bd7f,0xbd4e3d18,0x3d7b3c48,0xbd04bd5c,0xbc953d75,0x3d67bcdb,0xbd6dbcc4,0x3cac3d71,0x3cf1bd62,0xbd783c79,0x3d553d0e,0xbc16bd7d,0xbd223d46,0x3d80bb49,
0x3c48bd7b,0xbd713cac,0x3d463d22,0x3c16bd7d,0x3d353d35,0x3c79bd78,0xbd753c95,0x3d3e3d2c,0x3d553d0e,0x3b49bd80,0xbd623cf1,0x3d5c3d04,0xbd6d3cc4,0x3d4e3d18,0x3bc9bd7f,0xbd673cdb,
0x3d0e3d55,0x3cdbbd67,0xbd7f3bc9,0x3d183d4e,0xbd800000,0x3d043d5c,0x3cf1bd62,0xbd803b49,0xbd7b3c48,0x3d2c3d3e,0x3c95bd75,0xbd783c79,0x3cc4bd6d,0xbd7d3c16,0x3d223d46,0x3cacbd71,
0x3cc43d6d,0x3d3ebd2c,0xbd62bcf1,0xbc163d7d,0x3d7bbc48,0xbd04bd5c,0xbd223d46,0x3d713cac,0xbd35bd35,0xbcdb3d67,0x3d7f3bc9,0xbc79bd78,0xbd553d0e,0x3d4e3d18,0x3c95bd75,0xbd803b49,
0x3d6d3cc4,0x3b49bd80,0xbd753c95,0x3d183d4e,0x3d0ebd55,0xbd78bc79,0x3bc93d7f,0x3d67bcdb,0xbd800000,0x3cac3d71,0x3d46bd22,0xbd5cbd04,0xbc483d7b,0x3d7dbc16,0xbcf1bd62,0xbd2c3d3e,
0x3d0ebd55,0xbd67bcdb,0xbc953d75,0x3d7d3c16,0x3d6dbcc4,0xbd04bd5c,0xbd463d22,0x3d3e3d2c,0x3d7b3c48,0x3b49bd80,0xbd7f3bc9,0x3c793d78,0x3d353d35,0x3d18bd4e,0xbd62bcf1,0xbcac3d71,
0x3c483d7b,0x3d71bcac,0xbcf1bd62,0xbd4e3d18,0xbcc43d6d,0x3d783c79,0x3bc9bd7f,0xbd803b49,0xbd553d0e,0x3d2c3d3e,0x3d22bd46,0xbd5cbd04,0xbd800000,0x3c163d7d,0x3d75bc95,0xbcdbbd67,
0x3d80,0x3d803b49,0x3bc9bd7f,0xbd7dbc16,0xbc483d7b,0x3d783c79,0x3c95bd75,0xbd71bcac,0xbcc43d6d,0x3d673cdb,0x3cf1bd62,0xbd5cbd04,0xbd0e3d55,0x3d4e3d18,0x3d22bd46,0xbd3ebd2c,
0xbd353d35,0x3d2c3d3e,0x3d46bd22,0xbd18bd4e,0xbd553d0e,0x3d043d5c,0x3d62bcf1,0xbcdbbd67,0xbd6d3cc4,0x3cac3d71,0x3d75bc95,0xbc79bd78,0xbd7b3c48,0x3c163d7d,0x3d7fbbc9,0xbb49bd80,
0xbd553d0e,0x3cac3d71,0x3d7fbbc9,0x3c16bd7d,0x3d80,0x3d783c79,0x3cf1bd62,0xbd3ebd2c,0xbc48bd7b,0xbd80bb49,0xbc953d75,0x3d5c3d04,0xbd6dbcc4,0xbd183d4e,0x3d223d46,0x3d67bcdb,
0x3d7b3c48,0x3cdbbd67,0xbd46bd22,0xbd4e3d18,0x3d35bd35,0xbd04bd5c,0xbd753c95,0x3b493d80,0xbd0e3d55,0x3d2c3d3e,0x3d62bcf1,0xbc79bd78,0x3cc43d6d,0x3d7dbc16,0x3bc9bd7f,0xbd71bcac,
0x3cc4bd6d,0xbd2cbd3e,0xbd753c95,0xbc163d7d,0x3d553d0e,0x3d5cbd04,0xbbc9bd7f,0xbd71bcac,0x3d80,0x3d673cdb,0x3d46bd22,0xbc79bd78,0xbd7bbc48,0xbd183d4e,0x3cf13d62,0x3d80bb49,
0x3d6dbcc4,0x3b49bd80,0xbd62bcf1,0xbd4e3d18,0x3c483d7b,0x3d783c79,0x3d22bd46,0xbcdbbd67,0xbd353d35,0x3cac3d71,0x3d7f3bc9,0x3d04bd5c,0xbd0ebd55,0xbd7d3c16,0xbc953d75,0x3d3e3d2c,
0xbd7b3c48,0xbcdb3d67,0x3cf13d62,0x3d7d3c16,0x3d6d3cc4,0x3d5cbd04,0x3bc9bd7f,0xbd3ebd2c,0xbd0ebd55,0xbd80bb49,0xbd223d46,0x3c793d78,0x3d80,0x3d4e3d18,0x3d75bc95,0x3cacbd71,
0x3d553d0e,0x3d71bcac,0x3c95bd75,0xbd18bd4e,0xbcc4bd6d,0xbd78bc79,0xbd463d22,0x3b493d80,0xbc483d7b,0x3d2c3d3e,0x3d7fbbc9,0x3d04bd5c,0x3d35bd35,0xbc16bd7d,0xbd62bcf1,0xbd673cdb,
0xbd353d35,0xbb493d80,0x3d223d46,0x3d7d3c16,0x3d55bd0e,0x3c79bd78,0xbcf1bd62,0xbd71bcac,0xbd6d3cc4,0xbcdb3d67,0x3c953d75,0x3d5c3d04,0x3d7bbc48,0x3d18bd4e,0xbbc9bd7f,0xbd3ebd2c,
0x3d80,0x3d2c3d3e,0x3d7f3bc9,0x3d4ebd18,0x3c48bd7b,0xbd04bd5c,0xbd75bc95,0xbd673cdb,0xbcc43d6d,0x3cac3d71,0x3d623cf1,0x3d78bc79,0x3d0ebd55,0xbc16bd7d,0xbd46bd22,0xbd803b49,
0xbd7bbc48,0xbd713cac,0xbd223d46,0xbc163d7d,0x3d35bd35,0x3c79bd78,0xbc95bd75,0xbd3ebd2c,0x3d0ebd55,0x3b49bd80,0xbcf1bd62,0xbd5cbd04,0x3cc43d6d,0x3d4e3d18,0x3d7f3bc9,0x3d67bcdb,
0x3d55bd0e,0x3cdbbd67,0xbbc9bd7f,0xbd18bd4e,0x3d80,0x3d043d5c,0x3d623cf1,0x3d80bb49,0x3c483d7b,0x3d2c3d3e,0x3d753c95,0x3d78bc79,0xbd6dbcc4,0xbd7d3c16,0xbd463d22,0xbcac3d71,
0x3d6dbcc4,0x3d3ebd2c,0x3cf1bd62,0x3c16bd7d,0xbc48bd7b,0xbd04bd5c,0xbd46bd22,0xbd71bcac,0xbd353d35,0xbcdb3d67,0xbbc93d7f,0x3c793d78,0x3d0e3d55,0x3d4e3d18,0x3d753c95,0x3d80bb49,
0x3cc4bd6d,0x3b49bd80,0xbc95bd75,0xbd18bd4e,0xbd55bd0e,0xbd78bc79,0xbd7f3bc9,0xbd673cdb,0x3d80,0x3cac3d71,0x3d223d46,0x3d5c3d04,0x3d7b3c48,0x3d7dbc16,0x3d62bcf1,0x3d2cbd3e,
0xbd55bd0e,0xbd67bcdb,0xbd75bc95,0xbd7dbc16,0xbcc4bd6d,0xbd04bd5c,0xbd22bd46,0xbd3ebd2c,0x3c48bd7b,0x3b49bd80,0xbbc9bd7f,0xbc79bd78,0x3d35bd35,0x3d18bd4e,0x3cf1bd62,0x3cacbd71,
0x3d7bbc48,0x3d71bcac,0x3d62bcf1,0x3d4ebd18,0x3d6d3cc4,0x3d783c79,0x3d7f3bc9,0x3d80bb49,0x3d0e3d55,0x3d2c3d3e,0x3d463d22,0x3d5c3d04,0x3d80,0x3c163d7d,0x3c953d75,0x3cdb3d67,
0xbd800000,0xbb493d80,0x3d7f3bc9,0x3c16bd7d,0xbd7bbc48,0xbc793d78,0x3d753c95,0x3cacbd71,0xbd6dbcc4,0xbcdb3d67,0x3d623cf1,0x3d04bd5c,0xbd55bd0e,0xbd183d4e,0x3d463d22,0x3d2cbd3e,
0xbd35bd35,0xbd3e3d2c,0x3d223d46,0x3d4ebd18,0xbd0ebd55,0xbd5c3d04,0x3cf13d62,0x3d67bcdb,0xbcc4bd6d,0xbd713cac,0x3c953d75,0x3d78bc79,0xbc48bd7b,0xbd7d3c16,0x3bc93d7f,0x3d80bb49,
0xbd0ebd55,0xbd713cac,0x3bc93d7f,0x3d7d3c16,0xbd800000,0xbc793d78,0x3d623cf1,0x3d2cbd3e,0x3d7bbc48,0x3b49bd80,0xbd75bc95,0xbd043d5c,0x3cc4bd6d,0xbd4ebd18,0xbd463d22,0x3cdb3d67,
0xbc483d7b,0x3d673cdb,0x3d22bd46,0xbd18bd4e,0x3d353d35,0x3d5cbd04,0xbc95bd75,0xbd803b49,0xbd55bd0e,0xbd3e3d2c,0x3cf13d62,0x3d78bc79,0xbd6d3cc4,0x3c163d7d,0x3d7f3bc9,0x3cacbd71,
0x3d6d3cc4,0x3d3ebd2c,0xbc95bd75,0xbd7dbc16,0xbd0e3d55,0x3d043d5c,0x3d7fbbc9,0x3cacbd71,0xbd800000,0xbcdb3d67,0x3d223d46,0x3d78bc79,0x3c48bd7b,0xbd4ebd18,0xbd623cf1,0x3b493d80,
0x3cc43d6d,0x3d803b49,0x3cf1bd62,0xbd18bd4e,0xbd7b3c48,0xbc793d78,0x3d463d22,0x3d67bcdb,0xbd35bd35,0xbd713cac,0xbbc93d7f,0x3d5c3d04,0x3d55bd0e,0xbc16bd7d,0xbd75bc95,0xbd2c3d3e,
0xbc48bd7b,0xbd67bcdb,0xbd623cf1,0xbc163d7d,0xbcc43d6d,0x3d043d5c,0x3d7f3bc9,0x3d2cbd3e,0x3d55bd0e,0x3b49bd80,0xbd46bd22,0xbd783c79,0xbd800000,0xbd183d4e,0x3c953d75,0x3d713cac,
0xbd0e3d55,0x3cac3d71,0x3d753c95,0x3d4ebd18,0x3d6dbcc4,0x3c79bd78,0xbd22bd46,0xbd803b49,0xbd7bbc48,0xbd3e3d2c,0x3bc93d7f,0x3d5c3d04,0x3d353d35,0x3d7dbc16,0x3cf1bd62,0xbcdbbd67,
0xbd35bd35,0xbd80bb49,0xbd463d22,0xbc163d7d,0x3d0e3d55,0x3d783c79,0x3d62bcf1,0x3cacbd71,0xbcc4bd6d,0xbd67bcdb,0xbd753c95,0xbd043d5c,0x3c483d7b,0x3d4e3d18,0x3d7fbbc9,0x3d2cbd3e,
0xbd800000,0xbd3e3d2c,0xbbc93d7f,0x3d183d4e,0x3d7b3c48,0x3d5cbd04,0x3c95bd75,0xbcdbbd67,0xbd6dbcc4,0xbd713cac,0xbcf13d62,0x3c793d78,0x3d553d0e,0x3d7dbc16,0x3d22bd46,0xbb49bd80,
0x3c48bd7b,0xbcacbd71,0xbd46bd22,0xbd7dbc16,0x3d353d35,0x3d783c79,0x3d75bc95,0x3d2cbd3e,0x3d553d0e,0x3d803b49,0x3d62bcf1,0x3d04bd5c,0xbd6d3cc4,0xbd183d4e,0xbbc93d7f,0x3cdb3d67,
0x3d0e3d55,0x3d673cdb,0x3d7fbbc9,0x3d4ebd18,0xbd800000,0xbd5c3d04,0xbcf13d62,0x3b493d80,0xbd7b3c48,0xbd3e3d2c,0xbc953d75,0x3c793d78,0x3cc4bd6d,0xbc16bd7d,0xbd22bd46,0xbd71bcac,
0x3cc43d6d,0x3d2c3d3e,0x3d623cf1,0x3d7d3c16,0x3d7bbc48,0x3d5cbd04,0x3d22bd46,0x3cacbd71,0xbd35bd35,0xbd67bcdb,0xbd7fbbc9,0xbd783c79,0xbd553d0e,0xbd183d4e,0xbc953d75,0x3b493d80,
0x3d6d3cc4,0x3d803b49,0x3d75bc95,0x3d4ebd18,0x3d0ebd55,0x3c79bd78,0xbbc9bd7f,0xbcdbbd67,0xbd800000,0xbd713cac,0xbd463d22,0xbd043d5c,0xbc483d7b,0x3c163d7d,0x3cf13d62,0x3d3e3d2c,
0x3d0ebd55,0x3cdbbd67,0x3c95bd75,0x3c16bd7d,0x3d6dbcc4,0x3d5cbd04,0x3d46bd22,0x3d2cbd3e,0x3d7b3c48,0x3d803b49,0x3d7fbbc9,0x3d78bc79,0x3d353d35,0x3d4e3d18,0x3d623cf1,0x3d713cac,
0x3c483d7b,0x3cac3d71,0x3cf13d62,0x3d183d4e,0xbcc43d6d,0xbc793d78,0xbbc93d7f,0x3b493d80,0xbd553d0e,0xbd3e3d2c,0xbd223d46,0xbd043d5c,0xbd800000,0xbd7d3c16,0xbd753c95,0xbd673cdb,
0x3d80,0xbbc93d7f,0xbc483d7b,0xbc953d75,0xbcc43d6d,0xbcf13d62,0xbd0e3d55,0xbd223d46,0xbd353d35,0xbd463d22,0xbd553d0e,0xbd623cf1,0xbd6d3cc4,0xbd753c95,0xbd7b3c48,0xbd7f3bc9,
0xbd800000,0xbd7fbbc9,0xbd7bbc48,0xbd75bc95,0xbd6dbcc4,0xbd62bcf1,0xbd55bd0e,0xbd46bd22,0xbd35bd35,0xbd22bd46,0xbd0ebd55,0xbcf1bd62,0xbcc4bd6d,0xbc95bd75,0xbc48bd7b,0xbbc9bd7f,
0xbd6d3cc4,0xbd7f3bc9,0xbd7bbc48,0xbd62bcf1,0x3d80,0xbc953d75,0xbd0e3d55,0xbd463d22,0x3cc4bd6d,0x3d22bd46,0x3d55bd0e,0x3d75bc95,0xbd35bd35,0xbcf1bd62,0xbc48bd7b,0x3bc9bd7f,
0x3cc43d6d,0x3bc93d7f,0xbc483d7b,0xbcf13d62,0x3d800000,0x3d753c95,0x3d553d0e,0x3d223d46,0xbd6dbcc4,0xbd46bd22,0xbd0ebd55,0xbc95bd75,0xbd353d35,0xbd623cf1,0xbd7b3c48,0xbd7fbbc9,
0x3d35bd35,0x3d75bc95,0x3d7b3c48,0x3d463d22,0x3cc43d6d,0xbbc93d7f,0xbd0e3d55,0xbd623cf1,0x3d80,0xbcf13d62,0xbd553d0e,0xbd7f3bc9,0xbd6dbcc4,0xbd22bd46,0xbc48bd7b,0x3c95bd75,
0x3d353d35,0x3c953d75,0xbc483d7b,0xbd223d46,0xbd6d3cc4,0xbd7fbbc9,0xbd55bd0e,0xbcf1bd62,0xbd800000,0xbd62bcf1,0xbd0ebd55,0xbbc9bd7f,0x3cc4bd6d,0x3d46bd22,0x3d7bbc48,0x3d753c95,
0xbd6dbcc4,0xbcf1bd62,0x3c48bd7b,0x3d46bd22,0x3d353d35,0x3bc93d7f,0xbd0e3d55,0xbd753c95,0xbcc4bd6d,0x3c95bd75,0x3d55bd0e,0x3d7f3bc9,0x3d80,0xbd223d46,0xbd7b3c48,0xbd62bcf1,
0xbcc43d6d,0xbd623cf1,0xbd7bbc48,0xbd22bd46,0x3d35bd35,0x3d7fbbc9,0x3d553d0e,0x3c953d75,0xbd6d3cc4,0xbd75bc95,0xbd0ebd55,0x3bc9bd7f,0x3d800000,0x3d463d22,0x3c483d7b,0xbcf13d62,
0xbd800000,0xbd22bd46,0x3c48bd7b,0x3d62bcf1,0x3d6d3cc4,0x3c953d75,0xbd0e3d55,0xbd7f3bc9,0xbd35bd35,0x3bc9bd7f,0x3d55bd0e,0x3d753c95,0x3cc43d6d,0xbcf13d62,0xbd7b3c48,0xbd46bd22,
0x3d80,0xbd463d22,0xbd7bbc48,0xbcf1bd62,0x3cc4bd6d,0x3d75bc95,0x3d553d0e,0x3bc93d7f,0xbd353d35,0xbd7fbbc9,0xbd0ebd55,0x3c95bd75,0x3d6dbcc4,0x3d623cf1,0x3c483d7b,0xbd223d46,
0xbcc4bd6d,0x3d22bd46,0x3d7b3c48,0x3c953d75,0x3d800000,0x3cf13d62,0xbd0e3d55,0xbd7fbbc9,0x3d6d3cc4,0x3bc93d7f,0xbd553d0e,0xbd62bcf1,0xbd353d35,0xbd75bc95,0xbc48bd7b,0x3d46bd22,
0x3d6dbcc4,0x3d463d22,0xbc483d7b,0xbd753c95,0x3d80,0xbd623cf1,0xbd55bd0e,0x3bc9bd7f,0xbcc43d6d,0xbd7f3bc9,0xbd0ebd55,0x3cf1bd62,0xbd35bd35,0x3c95bd75,0x3d7bbc48,0x3d223d46,
0x3d353d35,0xbcf13d62,0xbd7bbc48,0xbbc9bd7f,0x3d6dbcc4,0x3d223d46,0xbd0e3d55,0xbd75bc95,0xbd800000,0xbc95bd75,0x3d55bd0e,0x3d463d22,0xbcc43d6d,0xbd7fbbc9,0xbc48bd7b,0x3d62bcf1,
0x3d35bd35,0x3d623cf1,0xbc483d7b,0xbd7f3bc9,0xbcc4bd6d,0x3d46bd22,0x3d553d0e,0xbc953d75,0x3d80,0xbd753c95,0xbd0ebd55,0x3d22bd46,0x3d6d3cc4,0xbbc93d7f,0xbd7b3c48,0xbcf1bd62,
0x3cc4bd6d,0x3d753c95,0xbc483d7b,0xbd7fbbc9,0x3d35bd35,0x3d463d22,0xbd0e3d55,0xbd62bcf1,0x3d6dbcc4,0x3cf13d62,0xbd553d0e,0xbd22bd46,0x3d800000,0x3bc93d7f,0xbd7b3c48,0xbc95bd75,
0x3d6d3cc4,0xbc953d75,0xbd7bbc48,0x3bc9bd7f,0x3d353d35,0xbd223d46,0xbd55bd0e,0x3cf1bd62,0x3cc43d6d,0xbd623cf1,0xbd0ebd55,0x3d46bd22,0x3d80,0xbd7f3bc9,0xbc48bd7b,0x3d75bc95,
0xbd800000,0xbd7fbbc9,0xbd7bbc48,0xbd75bc95,0xbd6dbcc4,0xbd62bcf1,0xbd55bd0e,0xbd46bd22,0xbd35bd35,0xbd22bd46,0xbd0ebd55,0xbcf1bd62,0xbcc4bd6d,0xbc95bd75,0xbc48bd7b,0xbbc9bd7f,
0x8000bd80,0x3bc9bd7f,0x3c48bd7b,0x3c95bd75,0x3cc4bd6d,0x3cf1bd62,0x3d0ebd55,0x3d22bd46,0x3d35bd35,0x3d46bd22,0x3d55bd0e,0x3d62bcf1,0x3d6dbcc4,0x3d75bc95,0x3d7bbc48,0x3d7fbbc9,
0xbcc4bd6d,0xbbc9bd7f,0x3c48bd7b,0x3cf1bd62,0xbd800000,0xbd75bc95,0xbd55bd0e,0xbd22bd46,0x3d6d3cc4,0x3d463d22,0x3d0e3d55,0x3c953d75,0x3d35bd35,0x3d62bcf1,0x3d7bbc48,0x3d7f3bc9,
0xbd6d3cc4,0xbd7f3bc9,0xbd7bbc48,0xbd62bcf1,0x80003d80,0xbc953d75,0xbd0e3d55,0xbd463d22,0x3cc4bd6d,0x3d22bd46,0x3d55bd0e,0x3d75bc95,0xbd35bd35,0xbcf1bd62,0xbc48bd7b,0x3bc9bd7f,
0x3d353d35,0x3c953d75,0xbc483d7b,0xbd223d46,0xbd6d3cc4,0xbd7fbbc9,0xbd55bd0e,0xbcf1bd62,0xbd800000,0xbd62bcf1,0xbd0ebd55,0xbbc9bd7f,0x3cc4bd6d,0x3d46bd22,0x3d7bbc48,0x3d753c95,
0xbd353d35,0xbd753c95,0xbd7bbc48,0xbd46bd22,0xbcc4bd6d,0x3bc9bd7f,0x3d0ebd55,0x3d62bcf1,0x8000bd80,0x3cf1bd62,0x3d55bd0e,0x3d7fbbc9,0x3d6d3cc4,0x3d223d46,0x3c483d7b,0xbc953d75,
0x3cc4bd6d,0x3d62bcf1,0x3d7b3c48,0x3d223d46,0xbd353d35,0xbd7f3bc9,0xbd55bd0e,0xbc95bd75,0x3d6dbcc4,0x3d753c95,0x3d0e3d55,0xbbc93d7f,0xbd800000,0xbd46bd22,0xbc48bd7b,0x3cf1bd62,
0xbd6dbcc4,0xbcf1bd62,0x3c48bd7b,0x3d46bd22,0x3d353d35,0x3bc93d7f,0xbd0e3d55,0xbd753c95,0xbcc4bd6d,0x3c95bd75,0x3d55bd0e,0x3d7f3bc9,0x80003d80,0xbd223d46,0xbd7b3c48,0xbd62bcf1,
0x8000bd80,0x3d46bd22,0x3d7b3c48,0x3cf13d62,0xbcc43d6d,0xbd753c95,0xbd55bd0e,0xbbc9bd7f,0x3d35bd35,0x3d7f3bc9,0x3d0e3d55,0xbc953d75,0xbd6d3cc4,0xbd62bcf1,0xbc48bd7b,0x3d22bd46,
0xbd800000,0xbd22bd46,0x3c48bd7b,0x3d62bcf1,0x3d6d3cc4,0x3c953d75,0xbd0e3d55,0xbd7f3bc9,0xbd35bd35,0x3bc9bd7f,0x3d55bd0e,0x3d753c95,0x3cc43d6d,0xbcf13d62,0xbd7b3c48,0xbd46bd22,
0x3d6dbcc4,0x3d463d22,0xbc483d7b,0xbd753c95,0x80003d80,0xbd623cf1,0xbd55bd0e,0x3bc9bd7f,0xbcc43d6d,0xbd7f3bc9,0xbd0ebd55,0x3cf1bd62,0xbd35bd35,0x3c95bd75,0x3d7bbc48,0x3d223d46,
0x3cc43d6d,0xbd223d46,0xbd7bbc48,0xbc95bd75,0xbd800000,0xbcf1bd62,0x3d0ebd55,0x3d7f3bc9,0xbd6dbcc4,0xbbc9bd7f,0x3d55bd0e,0x3d623cf1,0x3d35bd35,0x3d753c95,0x3c483d7b,0xbd463d22,
0xbd353d35,0xbd62bcf1,0x3c48bd7b,0x3d7fbbc9,0x3cc43d6d,0xbd463d22,0xbd55bd0e,0x3c95bd75,0x8000bd80,0x3d75bc95,0x3d0e3d55,0xbd223d46,0xbd6dbcc4,0x3bc9bd7f,0x3d7bbc48,0x3cf13d62,
0x3d353d35,0xbcf13d62,0xbd7bbc48,0xbbc9bd7f,0x3d6dbcc4,0x3d223d46,0xbd0e3d55,0xbd75bc95,0xbd800000,0xbc95bd75,0x3d55bd0e,0x3d463d22,0xbcc43d6d,0xbd7fbbc9,0xbc48bd7b,0x3d62bcf1,
0x3d6d3cc4,0xbc953d75,0xbd7bbc48,0x3bc9bd7f,0x3d353d35,0xbd223d46,0xbd55bd0e,0x3cf1bd62,0x3cc43d6d,0xbd623cf1,0xbd0ebd55,0x3d46bd22,0x80003d80,0xbd7f3bc9,0xbc48bd7b,0x3d75bc95,
0xbcc43d6d,0xbd75bc95,0x3c48bd7b,0x3d7f3bc9,0xbd353d35,0xbd46bd22,0x3d0ebd55,0x3d623cf1,0xbd6d3cc4,0xbcf1bd62,0x3d55bd0e,0x3d223d46,0xbd800000,0xbbc9bd7f,0x3d7bbc48,0x3c953d75,
0x3d80,0xbd7fbbc9,0x3c48bd7b,0x3d753c95,0xbcc43d6d,0xbd62bcf1,0x3d0ebd55,0x3d463d22,0xbd353d35,0xbd22bd46,0x3d55bd0e,0x3cf13d62,0xbd6d3cc4,0xbc95bd75,0x3d7bbc48,0x3bc93d7f,
0xbd800000,0x3bc9bd7f,0x3d7b3c48,0xbc953d75,0xbd6dbcc4,0x3cf1bd62,0x3d553d0e,0xbd223d46,0xbd35bd35,0x3d46bd22,0x3d0e3d55,0xbd623cf1,0xbcc4bd6d,0x3d75bc95,0x3c483d7b,0xbd7f3bc9,
0xbd6d3cc4,0xbbc9bd7f,0x3d7b3c48,0xbcf13d62,0x3d80,0xbd75bc95,0x3d0ebd55,0x3d223d46,0x3cc4bd6d,0x3d463d22,0xbd553d0e,0xbc95bd75,0xbd35bd35,0x3d62bcf1,0x3c483d7b,0xbd7fbbc9,
0x3cc43d6d,0xbd7f3bc9,0x3c48bd7b,0x3d623cf1,0x3d800000,0xbc953d75,0xbd55bd0e,0x3d46bd22,0xbd6dbcc4,0x3d22bd46,0x3d0e3d55,0xbd753c95,0xbd353d35,0xbcf1bd62,0x3d7bbc48,0xbbc93d7f,
0x3d35bd35,0x3c953d75,0xbd7bbc48,0x3d22bd46,0x3cc43d6d,0xbd7fbbc9,0x3d0ebd55,0x3cf13d62,0x3d80,0xbd62bcf1,0x3d55bd0e,0x3bc93d7f,0xbd6dbcc4,0x3d46bd22,0x3c483d7b,0xbd75bc95,
0x3d353d35,0xbd753c95,0x3c48bd7b,0x3d463d22,0xbd6d3cc4,0x3bc9bd7f,0x3d553d0e,0xbd623cf1,0xbd800000,0x3cf1bd62,0x3d0e3d55,0xbd7f3bc9,0x3cc4bd6d,0x3d223d46,0xbd7b3c48,0x3c95bd75,
0xbd6dbcc4,0x3d62bcf1,0xbc483d7b,0xbd22bd46,0x3d353d35,0xbd7f3bc9,0x3d0ebd55,0x3c953d75,0xbcc4bd6d,0x3d753c95,0xbd553d0e,0x3bc9bd7f,0x3d80,0xbd46bd22,0x3d7bbc48,0xbcf13d62,
0xbcc43d6d,0xbcf1bd62,0x3d7b3c48,0xbd463d22,0x3d35bd35,0x3bc93d7f,0xbd55bd0e,0x3d75bc95,0xbd6d3cc4,0x3c95bd75,0x3d0e3d55,0xbd7fbbc9,0x3d800000,0xbd223d46,0xbc48bd7b,0x3d623cf1,
0xbd800000,0x3d46bd22,0xbc483d7b,0xbcf1bd62,0x3d6d3cc4,0xbd753c95,0x3d0ebd55,0x3bc93d7f,0xbd35bd35,0x3d7f3bc9,0xbd553d0e,0x3c95bd75,0x3cc43d6d,0xbd62bcf1,0x3d7bbc48,0xbd223d46,
0x3d80,0xbd22bd46,0x3d7b3c48,0xbd623cf1,0x3cc4bd6d,0x3c953d75,0xbd55bd0e,0x3d7fbbc9,0xbd353d35,0x3bc9bd7f,0x3d0e3d55,0xbd75bc95,0x3d6dbcc4,0xbcf13d62,0xbc48bd7b,0x3d463d22,
0xbcc4bd6d,0x3d463d22,0xbd7bbc48,0x3d75bc95,0x3d800000,0xbd623cf1,0x3d0ebd55,0xbbc93d7f,0x3d6d3cc4,0xbd7f3bc9,0x3d55bd0e,0xbcf13d62,0xbd353d35,0x3c95bd75,0x3c483d7b,0xbd22bd46,
0x3d6dbcc4,0xbd223d46,0x3c48bd7b,0x3c953d75,0x3d80,0xbcf1bd62,0x3d553d0e,0xbd7fbbc9,0xbcc43d6d,0xbbc9bd7f,0x3d0e3d55,0xbd62bcf1,0xbd35bd35,0x3d753c95,0xbd7b3c48,0x3d46bd22,
0x3d353d35,0xbd62bcf1,0x3d7b3c48,0xbd7f3bc9,0x3d6dbcc4,0xbd463d22,0x3d0ebd55,0xbc953d75,0xbd800000,0x3d75bc95,0xbd553d0e,0x3d22bd46,0xbcc43d6d,0x3bc9bd7f,0x3c483d7b,0xbcf1bd62,
0x3d35bd35,0xbcf13d62,0x3c48bd7b,0x3bc93d7f,0xbcc4bd6d,0x3d223d46,0xbd55bd0e,0x3d753c95,0x3d80,0xbc95bd75,0x3d0e3d55,0xbd46bd22,0x3d6d3cc4,0xbd7fbbc9,0x3d7bbc48,0xbd623cf1,
0x3cc4bd6d,0xbc953d75,0x3c48bd7b,0xbbc93d7f,0x3d35bd35,0xbd223d46,0x3d0ebd55,0xbcf13d62,0x3d6dbcc4,0xbd623cf1,0x3d55bd0e,0xbd463d22,0x3d800000,0xbd7f3bc9,0x3d7bbc48,0xbd753c95,
0x3d6d3cc4,0xbd75bc95,0x3d7b3c48,0xbd7fbbc9,0x3d353d35,0xbd46bd22,0x3d553d0e,0xbd62bcf1,0x3cc43d6d,0xbcf1bd62,0x3d0e3d55,0xbd22bd46,0x3d80,0xbbc9bd7f,0x3c483d7b,0xbc95bd75,
0xbd800000,0x3bc9bd7f,0x3d7b3c48,0xbc953d75,0xbd6dbcc4,0x3cf1bd62,0x3d553d0e,0xbd223d46,0xbd35bd35,0x3d46bd22,0x3d0e3d55,0xbd623cf1,0xbcc4bd6d,0x3d75bc95,0x3c483d7b,0xbd7f3bc9,
0x8000bd80,0x3d7f3bc9,0xbc483d7b,0xbd75bc95,0x3cc4bd6d,0x3d623cf1,0xbd0e3d55,0xbd46bd22,0x3d35bd35,0x3d223d46,0xbd553d0e,0xbcf1bd62,0x3d6dbcc4,0x3c953d75,0xbd7b3c48,0xbbc9bd7f,
0xbcc4bd6d,0x3d7fbbc9,0xbc483d7b,0xbd62bcf1,0xbd800000,0x3c95bd75,0x3d553d0e,0xbd463d22,0x3d6d3cc4,0xbd223d46,0xbd0ebd55,0x3d75bc95,0x3d35bd35,0x3cf13d62,0xbd7b3c48,0x3bc9bd7f,
0xbd6d3cc4,0xbbc9bd7f,0x3d7b3c48,0xbcf13d62,0x80003d80,0xbd75bc95,0x3d0ebd55,0x3d223d46,0x3cc4bd6d,0x3d463d22,0xbd553d0e,0xbc95bd75,0xbd35bd35,0x3d62bcf1,0x3c483d7b,0xbd7fbbc9,
0x3d353d35,0xbd753c95,0x3c48bd7b,0x3d463d22,0xbd6d3cc4,0x3bc9bd7f,0x3d553d0e,0xbd623cf1,0xbd800000,0x3cf1bd62,0x3d0e3d55,0xbd7f3bc9,0x3cc4bd6d,0x3d223d46,0xbd7b3c48,0x3c95bd75,
0xbd353d35,0xbc95bd75,0x3d7b3c48,0xbd223d46,0xbcc4bd6d,0x3d7f3bc9,0xbd0e3d55,0xbcf1bd62,0x8000bd80,0x3d623cf1,0xbd553d0e,0xbbc9bd7f,0x3d6d3cc4,0xbd463d22,0xbc48bd7b,0x3d753c95,
0x3cc4bd6d,0x3cf13d62,0xbd7bbc48,0x3d46bd22,0xbd353d35,0xbbc9bd7f,0x3d553d0e,0xbd753c95,0x3d6dbcc4,0xbc953d75,0xbd0ebd55,0x3d7f3bc9,0xbd800000,0x3d22bd46,0x3c483d7b,0xbd62bcf1,
0xbd6dbcc4,0x3d62bcf1,0xbc483d7b,0xbd22bd46,0x3d353d35,0xbd7f3bc9,0x3d0ebd55,0x3c953d75,0xbcc4bd6d,0x3d753c95,0xbd553d0e,0x3bc9bd7f,0x80003d80,0xbd46bd22,0x3d7bbc48,0xbcf13d62,
0x8000bd80,0x3d223d46,0xbd7bbc48,0x3d62bcf1,0xbcc43d6d,0xbc95bd75,0x3d553d0e,0xbd7f3bc9,0x3d35bd35,0xbbc93d7f,0xbd0ebd55,0x3d753c95,0xbd6d3cc4,0x3cf1bd62,0x3c483d7b,0xbd46bd22,
0xbd800000,0x3d46bd22,0xbc483d7b,0xbcf1bd62,0x3d6d3cc4,0xbd753c95,0x3d0ebd55,0x3bc93d7f,0xbd35bd35,0x3d7f3bc9,0xbd553d0e,0x3c95bd75,0x3cc43d6d,0xbd62bcf1,0x3d7bbc48,0xbd223d46,
0x3d6dbcc4,0xbd223d46,0x3c48bd7b,0x3c953d75,0x80003d80,0xbcf1bd62,0x3d553d0e,0xbd7fbbc9,0xbcc43d6d,0xbbc9bd7f,0x3d0e3d55,0xbd62bcf1,0xbd35bd35,0x3d753c95,0xbd7b3c48,0x3d46bd22,
0x3cc43d6d,0xbd46bd22,0x3d7b3c48,0xbd753c95,0xbd800000,0x3d62bcf1,0xbd0e3d55,0x3bc9bd7f,0xbd6dbcc4,0x3d7fbbc9,0xbd553d0e,0x3cf1bd62,0x3d35bd35,0xbc953d75,0xbc48bd7b,0x3d223d46,
0xbd353d35,0x3cf1bd62,0xbc483d7b,0xbbc9bd7f,0x3cc43d6d,0xbd22bd46,0x3d553d0e,0xbd75bc95,0x8000bd80,0x3c953d75,0xbd0ebd55,0x3d463d22,0xbd6dbcc4,0x3d7f3bc9,0xbd7b3c48,0x3d62bcf1,
0x3d353d35,0xbd62bcf1,0x3d7b3c48,0xbd7f3bc9,0x3d6dbcc4,0xbd463d22,0x3d0ebd55,0xbc953d75,0xbd800000,0x3d75bc95,0xbd553d0e,0x3d22bd46,0xbcc43d6d,0x3bc9bd7f,0x3c483d7b,0xbcf1bd62,
0x3d6d3cc4,0xbd75bc95,0x3d7b3c48,0xbd7fbbc9,0x3d353d35,0xbd46bd22,0x3d553d0e,0xbd62bcf1,0x3cc43d6d,0xbcf1bd62,0x3d0e3d55,0xbd22bd46,0x80003d80,0xbbc9bd7f,0x3c483d7b,0xbc95bd75,
0xbcc43d6d,0x3c95bd75,0xbc483d7b,0x3bc9bd7f,0xbd353d35,0x3d22bd46,0xbd0e3d55,0x3cf1bd62,0xbd6d3cc4,0x3d62bcf1,0xbd553d0e,0x3d46bd22,0xbd800000,0x3d7fbbc9,0xbd7b3c48,0x3d75bc95,
0x3d80,0x3bc9bd7f,0xbc483d7b,0x3c95bd75,0xbcc43d6d,0x3cf1bd62,0xbd0e3d55,0x3d22bd46,0xbd353d35,0x3d46bd22,0xbd553d0e,0x3d62bcf1,0xbd6d3cc4,0x3d75bc95,0xbd7b3c48,0x3d7fbbc9,
0xbd800000,0x3d7f3bc9,0xbd7bbc48,0x3d753c95,0xbd6dbcc4,0x3d623cf1,0xbd55bd0e,0x3d463d22,0xbd35bd35,0x3d223d46,0xbd0ebd55,0x3cf13d62,0xbcc4bd6d,0x3c953d75,0xbc48bd7b,0x3bc93d7f,
0xbd6d3cc4,0x3d7fbbc9,0xbd7bbc48,0x3d623cf1,0x3d80,0x3c95bd75,0xbd0e3d55,0x3d46bd22,0x3cc4bd6d,0xbd223d46,0x3d55bd0e,0xbd753c95,0xbd35bd35,0x3cf13d62,0xbc48bd7b,0xbbc93d7f,
0x3cc43d6d,0xbbc9bd7f,0xbc483d7b,0x3cf1bd62,0x3d800000,0xbd75bc95,0x3d553d0e,0xbd22bd46,0xbd6dbcc4,0x3d463d22,0xbd0ebd55,0x3c953d75,0xbd353d35,0x3d62bcf1,0xbd7b3c48,0x3d7f3bc9,
0x3d35bd35,0xbd753c95,0x3d7b3c48,0xbd46bd22,0x3cc43d6d,0x3bc9bd7f,0xbd0e3d55,0x3d62bcf1,0x3d80,0x3cf1bd62,0xbd553d0e,0x3d7fbbc9,0xbd6dbcc4,0x3d223d46,0xbc48bd7b,0xbc953d75,
0x3d353d35,0xbc95bd75,0xbc483d7b,0x3d22bd46,0xbd6d3cc4,0x3d7f3bc9,0xbd55bd0e,0x3cf13d62,0xbd800000,0x3d623cf1,0xbd0ebd55,0x3bc93d7f,0x3cc4bd6d,0xbd463d22,0x3d7bbc48,0xbd75bc95,
0xbd6dbcc4,0x3cf13d62,0x3c48bd7b,0xbd463d22,0x3d353d35,0xbbc9bd7f,0xbd0e3d55,0x3d75bc95,0xbcc4bd6d,0xbc953d75,0x3d55bd0e,0xbd7fbbc9,0x3d80,0x3d22bd46,0xbd7b3c48,0x3d623cf1,
0xbcc43d6d,0x3d62bcf1,0xbd7bbc48,0x3d223d46,0x3d35bd35,0xbd7f3bc9,0x3d553d0e,0xbc95bd75,0xbd6d3cc4,0x3d753c95,0xbd0ebd55,0xbbc93d7f,0x3d800000,0xbd46bd22,0x3c483d7b,0x3cf1bd62,
0xbd800000,0x3d223d46,0x3c48bd7b,0xbd623cf1,0x3d6d3cc4,0xbc95bd75,0xbd0e3d55,0x3d7fbbc9,0xbd35bd35,0xbbc93d7f,0x3d55bd0e,0xbd75bc95,0x3cc43d6d,0x3cf1bd62,0xbd7b3c48,0x3d463d22,
0x3d80,0x3d46bd22,0xbd7bbc48,0x3cf13d62,0x3cc4bd6d,0xbd753c95,0x3d553d0e,0xbbc9bd7f,0xbd353d35,0x3d7f3bc9,0xbd0ebd55,0xbc953d75,0x3d6dbcc4,0xbd62bcf1,0x3c483d7b,0x3d22bd46,
0xbcc4bd6d,0xbd223d46,0x3d7b3c48,0xbc95bd75,0x3d800000,0xbcf1bd62,0xbd0e3d55,0x3d7f3bc9,0x3d6d3cc4,0xbbc9bd7f,0xbd553d0e,0x3d623cf1,0xbd353d35,0x3d753c95,0xbc48bd7b,0xbd463d22,
0x3d6dbcc4,0xbd46bd22,0xbc483d7b,0x3d75bc95,0x3d80,0x3d62bcf1,0xbd55bd0e,0xbbc93d7f,0xbcc43d6d,0x3d7fbbc9,0xbd0ebd55,0xbcf13d62,0xbd35bd35,0xbc953d75,0x3d7bbc48,0xbd22bd46,
0x3d353d35,0x3cf1bd62,0xbd7bbc48,0x3bc93d7f,0x3d6dbcc4,0xbd22bd46,0xbd0e3d55,0x3d753c95,0xbd800000,0x3c953d75,0x3d55bd0e,0xbd46bd22,0xbcc43d6d,0x3d7f3bc9,0xbc48bd7b,0xbd623cf1,
0x3d35bd35,0xbd62bcf1,0xbc483d7b,0x3d7fbbc9,0xbcc4bd6d,0xbd463d22,0x3d553d0e,0x3c95bd75,0x3d80,0x3d75bc95,0xbd0ebd55,0xbd223d46,0x3d6d3cc4,0x3bc9bd7f,0xbd7b3c48,0x3cf13d62,
0x3cc4bd6d,0xbd75bc95,0xbc483d7b,0x3d7f3bc9,0x3d35bd35,0xbd46bd22,0xbd0e3d55,0x3d623cf1,0x3d6dbcc4,0xbcf1bd62,0xbd553d0e,0x3d223d46,0x3d800000,0xbbc9bd7f,0xbd7b3c48,0x3c953d75,
0x3d6d3cc4,0x3c95bd75,0xbd7bbc48,0xbbc93d7f,0x3d353d35,0x3d22bd46,0xbd55bd0e,0xbcf13d62,0x3cc43d6d,0x3d62bcf1,0xbd0ebd55,0xbd463d22,0x3d80,0x3d7fbbc9,0xbc48bd7b,0xbd753c95,
0xbd800000,0x3d7f3bc9,0xbd7bbc48,0x3d753c95,0xbd6dbcc4,0x3d623cf1,0xbd55bd0e,0x3d463d22,0xbd35bd35,0x3d223d46,0xbd0ebd55,0x3cf13d62,0xbcc4bd6d,0x3c953d75,0xbc48bd7b,0x3bc93d7f,
0x8000bd80,0xbbc93d7f,0x3c48bd7b,0xbc953d75,0x3cc4bd6d,0xbcf13d62,0x3d0ebd55,0xbd223d46,0x3d35bd35,0xbd463d22,0x3d55bd0e,0xbd623cf1,0x3d6dbcc4,0xbd753c95,0x3d7bbc48,0xbd7f3bc9,
0xbcc4bd6d,0x3bc93d7f,0x3c48bd7b,0xbcf13d62,0xbd800000,0x3d753c95,0xbd55bd0e,0x3d223d46,0x3d6d3cc4,0xbd46bd22,0x3d0e3d55,0xbc95bd75,0x3d35bd35,0xbd623cf1,0x3d7bbc48,0xbd7fbbc9,
0xbd6d3cc4,0x3d7fbbc9,0xbd7bbc48,0x3d623cf1,0x80003d80,0x3c95bd75,0xbd0e3d55,0x3d46bd22,0x3cc4bd6d,0xbd223d46,0x3d55bd0e,0xbd753c95,0xbd35bd35,0x3cf13d62,0xbc48bd7b,0xbbc93d7f,
0x3d353d35,0xbc95bd75,0xbc483d7b,0x3d22bd46,0xbd6d3cc4,0x3d7f3bc9,0xbd55bd0e,0x3cf13d62,0xbd800000,0x3d623cf1,0xbd0ebd55,0x3bc93d7f,0x3cc4bd6d,0xbd463d22,0x3d7bbc48,0xbd75bc95,
0xbd353d35,0x3d75bc95,0xbd7bbc48,0x3d463d22,0xbcc4bd6d,0xbbc93d7f,0x3d0ebd55,0xbd623cf1,0x8000bd80,0xbcf13d62,0x3d55bd0e,0xbd7f3bc9,0x3d6d3cc4,0xbd22bd46,0x3c483d7b,0x3c95bd75,
0x3cc4bd6d,0xbd623cf1,0x3d7b3c48,0xbd22bd46,0xbd353d35,0x3d7fbbc9,0xbd55bd0e,0x3c953d75,0x3d6dbcc4,0xbd75bc95,0x3d0e3d55,0x3bc9bd7f,0xbd800000,0x3d463d22,0xbc48bd7b,0xbcf13d62,
0xbd6dbcc4,0x3cf13d62,0x3c48bd7b,0xbd463d22,0x3d353d35,0xbbc9bd7f,0xbd0e3d55,0x3d75bc95,0xbcc4bd6d,0xbc953d75,0x3d55bd0e,0xbd7fbbc9,0x80003d80,0x3d22bd46,0xbd7b3c48,0x3d623cf1,
0x8000bd80,0xbd463d22,0x3d7b3c48,0xbcf1bd62,0xbcc43d6d,0x3d75bc95,0xbd55bd0e,0x3bc93d7f,0x3d35bd35,0xbd7fbbc9,0x3d0e3d55,0x3c95bd75,0xbd6d3cc4,0x3d623cf1,0xbc48bd7b,0xbd223d46,
0xbd800000,0x3d223d46,0x3c48bd7b,0xbd623cf1,0x3d6d3cc4,0xbc95bd75,0xbd0e3d55,0x3d7fbbc9,0xbd35bd35,0xbbc93d7f,0x3d55bd0e,0xbd75bc95,0x3cc43d6d,0x3cf1bd62,0xbd7b3c48,0x3d463d22,
0x3d6dbcc4,0xbd46bd22,0xbc483d7b,0x3d75bc95,0x80003d80,0x3d62bcf1,0xbd55bd0e,0xbbc93d7f,0xbcc43d6d,0x3d7fbbc9,0xbd0ebd55,0xbcf13d62,0xbd35bd35,0xbc953d75,0x3d7bbc48,0xbd22bd46,
0x3cc43d6d,0x3d22bd46,0xbd7bbc48,0x3c953d75,0xbd800000,0x3cf13d62,0x3d0ebd55,0xbd7fbbc9,0xbd6dbcc4,0x3bc93d7f,0x3d55bd0e,0xbd62bcf1,0x3d35bd35,0xbd75bc95,0x3c483d7b,0x3d46bd22,
0xbd353d35,0x3d623cf1,0x3c48bd7b,0xbd7f3bc9,0x3cc43d6d,0x3d46bd22,0xbd55bd0e,0xbc953d75,0x8000bd80,0xbd753c95,0x3d0e3d55,0x3d22bd46,0xbd6dbcc4,0xbbc93d7f,0x3d7bbc48,0xbcf1bd62,
0x3d353d35,0x3cf1bd62,0xbd7bbc48,0x3bc93d7f,0x3d6dbcc4,0xbd22bd46,0xbd0e3d55,0x3d753c95,0xbd800000,0x3c953d75,0x3d55bd0e,0xbd46bd22,0xbcc43d6d,0x3d7f3bc9,0xbc48bd7b,0xbd623cf1,
0x3d6d3cc4,0x3c95bd75,0xbd7bbc48,0xbbc93d7f,0x3d353d35,0x3d22bd46,0xbd55bd0e,0xbcf13d62,0x3cc43d6d,0x3d62bcf1,0xbd0ebd55,0xbd463d22,0x80003d80,0x3d7fbbc9,0xbc48bd7b,0xbd753c95,
0xbcc43d6d,0x3d753c95,0x3c48bd7b,0xbd7fbbc9,0xbd353d35,0x3d463d22,0x3d0ebd55,0xbd62bcf1,0xbd6d3cc4,0x3cf13d62,0x3d55bd0e,0xbd22bd46,0xbd800000,0x3bc93d7f,0x3d7bbc48,0xbc95bd75,
0x3d80,0x3d7f3bc9,0x3c48bd7b,0xbd75bc95,0xbcc43d6d,0x3d623cf1,0x3d0ebd55,0xbd46bd22,0xbd353d35,0x3d223d46,0x3d55bd0e,0xbcf1bd62,0xbd6d3cc4,0x3c953d75,0x3d7bbc48,0xbbc9bd7f,
0xbd800000,0xbbc93d7f,0x3d7b3c48,0x3c95bd75,0xbd6dbcc4,0xbcf13d62,0x3d553d0e,0x3d22bd46,0xbd35bd35,0xbd463d22,0x3d0e3d55,0x3d62bcf1,0xbcc4bd6d,0xbd753c95,0x3c483d7b,0x3d7fbbc9,
0xbd6d3cc4,0x3bc93d7f,0x3d7b3c48,0x3cf1bd62,0x3d80,0x3d753c95,0x3d0ebd55,0xbd22bd46,0x3cc4bd6d,0xbd46bd22,0xbd553d0e,0x3c953d75,0xbd35bd35,0xbd623cf1,0x3c483d7b,0x3d7f3bc9,
0x3cc43d6d,0x3d7fbbc9,0x3c48bd7b,0xbd62bcf1,0x3d800000,0x3c95bd75,0xbd55bd0e,0xbd463d22,0xbd6dbcc4,0xbd223d46,0x3d0e3d55,0x3d75bc95,0xbd353d35,0x3cf13d62,0x3d7bbc48,0x3bc9bd7f,
0x3d35bd35,0xbc95bd75,0xbd7bbc48,0xbd223d46,0x3cc43d6d,0x3d7f3bc9,0x3d0ebd55,0xbcf1bd62,0x3d80,0x3d623cf1,0x3d55bd0e,0xbbc9bd7f,0xbd6dbcc4,0xbd463d22,0x3c483d7b,0x3d753c95,
0x3d353d35,0x3d75bc95,0x3c48bd7b,0xbd46bd22,0xbd6d3cc4,0xbbc93d7f,0x3d553d0e,0x3d62bcf1,0xbd800000,0xbcf13d62,0x3d0e3d55,0x3d7fbbc9,0x3cc4bd6d,0xbd22bd46,0xbd7b3c48,0xbc953d75,
0xbd6dbcc4,0xbd623cf1,0xbc483d7b,0x3d223d46,0x3d353d35,0x3d7fbbc9,0x3d0ebd55,0xbc95bd75,0xbcc4bd6d,0xbd75bc95,0xbd553d0e,0xbbc93d7f,0x3d80,0x3d463d22,0x3d7bbc48,0x3cf1bd62,
0xbcc43d6d,0x3cf13d62,0x3d7b3c48,0x3d46bd22,0x3d35bd35,0xbbc9bd7f,0xbd55bd0e,0xbd753c95,0xbd6d3cc4,0xbc953d75,0x3d0e3d55,0x3d7f3bc9,0x3d800000,0x3d22bd46,0xbc48bd7b,0xbd62bcf1,
0xbd800000,0xbd463d22,0xbc483d7b,0x3cf13d62,0x3d6d3cc4,0x3d75bc95,0x3d0ebd55,0xbbc9bd7f,0xbd35bd35,0xbd7fbbc9,0xbd553d0e,0xbc953d75,0x3cc43d6d,0x3d623cf1,0x3d7bbc48,0x3d22bd46,
0x3d80,0x3d223d46,0x3d7b3c48,0x3d62bcf1,0x3cc4bd6d,0xbc95bd75,0xbd55bd0e,0xbd7f3bc9,0xbd353d35,0xbbc93d7f,0x3d0e3d55,0x3d753c95,0x3d6dbcc4,0x3cf1bd62,0xbc48bd7b,0xbd46bd22,
0xbcc4bd6d,0xbd46bd22,0xbd7bbc48,0xbd753c95,0x3d800000,0x3d62bcf1,0x3d0ebd55,0x3bc9bd7f,0x3d6d3cc4,0x3d7fbbc9,0x3d55bd0e,0x3cf1bd62,0xbd353d35,0xbc953d75,0x3c483d7b,0x3d223d46,
0x3d6dbcc4,0x3d22bd46,0x3c48bd7b,0xbc95bd75,0x3d80,0x3cf13d62,0x3d553d0e,0x3d7f3bc9,0xbcc43d6d,0x3bc93d7f,0x3d0e3d55,0x3d623cf1,0xbd35bd35,0xbd75bc95,0xbd7b3c48,0xbd463d22,
0x3d353d35,0x3d623cf1,0x3d7b3c48,0x3d7fbbc9,0x3d6dbcc4,0x3d46bd22,0x3d0ebd55,0x3c95bd75,0xbd800000,0xbd753c95,0xbd553d0e,0xbd223d46,0xbcc43d6d,0xbbc93d7f,0x3c483d7b,0x3cf13d62,
0x3d35bd35,0x3cf1bd62,0x3c48bd7b,0xbbc9bd7f,0xbcc4bd6d,0xbd22bd46,0xbd55bd0e,0xbd75bc95,0x3d80,0x3c953d75,0x3d0e3d55,0x3d463d22,0x3d6d3cc4,0x3d7f3bc9,0x3d7bbc48,0x3d62bcf1,
0x3cc4bd6d,0x3c95bd75,0x3c48bd7b,0x3bc9bd7f,0x3d35bd35,0x3d22bd46,0x3d0ebd55,0x3cf1bd62,0x3d6dbcc4,0x3d62bcf1,0x3d55bd0e,0x3d46bd22,0x3d800000,0x3d7fbbc9,0x3d7bbc48,0x3d75bc95,
0x3d6d3cc4,0x3d753c95,0x3d7b3c48,0x3d7f3bc9,0x3d353d35,0x3d463d22,0x3d553d0e,0x3d623cf1,0x3cc43d6d,0x3cf13d62,0x3d0e3d55,0x3d223d46,0x3d80,0x3bc93d7f,0x3c483d7b,0x3c953d75,
0xbd800000,0xbbc93d7f,0x3d7b3c48,0x3c95bd75,0xbd6dbcc4,0xbcf13d62,0x3d553d0e,0x3d22bd46,0xbd35bd35,0xbd463d22,0x3d0e3d55,0x3d62bcf1,0xbcc4bd6d,0xbd753c95,0x3c483d7b,0x3d7fbbc9,
0x8000bd80,0xbd7fbbc9,0xbc483d7b,0x3d753c95,0x3cc4bd6d,0xbd62bcf1,0xbd0e3d55,0x3d463d22,0x3d35bd35,0xbd22bd46,0xbd553d0e,0x3cf13d62,0x3d6dbcc4,0xbc95bd75,0xbd7b3c48,0x3bc93d7f,
0xbcc4bd6d,0xbd7f3bc9,0xbc483d7b,0x3d623cf1,0xbd800000,0xbc953d75,0x3d553d0e,0x3d46bd22,0x3d6d3cc4,0x3d22bd46,0xbd0ebd55,0xbd753c95,0x3d35bd35,0xbcf1bd62,0xbd7b3c48,0xbbc93d7f,
0xbd6d3cc4,0x3bc93d7f,0x3d7b3c48,0x3cf1bd62,0x80003d80,0x3d753c95,0x3d0ebd55,0xbd22bd46,0x3cc4bd6d,0xbd46bd22,0xbd553d0e,0x3c953d75,0xbd35bd35,0xbd623cf1,0x3c483d7b,0x3d7f3bc9,
0x3d353d35,0x3d75bc95,0x3c48bd7b,0xbd46bd22,0xbd6d3cc4,0xbbc93d7f,0x3d553d0e,0x3d62bcf1,0xbd800000,0xbcf13d62,0x3d0e3d55,0x3d7fbbc9,0x3cc4bd6d,0xbd22bd46,0xbd7b3c48,0xbc953d75,
0xbd353d35,0x3c953d75,0x3d7b3c48,0x3d22bd46,0xbcc4bd6d,0xbd7fbbc9,0xbd0e3d55,0x3cf13d62,0x8000bd80,0xbd62bcf1,0xbd553d0e,0x3bc93d7f,0x3d6d3cc4,0x3d46bd22,0xbc48bd7b,0xbd75bc95,
0x3cc4bd6d,0xbcf1bd62,0xbd7bbc48,0xbd463d22,0xbd353d35,0x3bc93d7f,0x3d553d0e,0x3d75bc95,0x3d6dbcc4,0x3c95bd75,0xbd0ebd55,0xbd7fbbc9,0xbd800000,0xbd223d46,0x3c483d7b,0x3d623cf1,
0xbd6dbcc4,0xbd623cf1,0xbc483d7b,0x3d223d46,0x3d353d35,0x3d7fbbc9,0x3d0ebd55,0xbc95bd75,0xbcc4bd6d,0xbd75bc95,0xbd553d0e,0xbbc93d7f,0x80003d80,0x3d463d22,0x3d7bbc48,0x3cf1bd62,
0x8000bd80,0xbd22bd46,0xbd7bbc48,0xbd623cf1,0xbcc43d6d,0x3c953d75,0x3d553d0e,0x3d7fbbc9,0x3d35bd35,0x3bc9bd7f,0xbd0ebd55,0xbd75bc95,0xbd6d3cc4,0xbcf13d62,0x3c483d7b,0x3d463d22,
0xbd800000,0xbd463d22,0xbc483d7b,0x3cf13d62,0x3d6d3cc4,0x3d75bc95,0x3d0ebd55,0xbbc9bd7f,0xbd35bd35,0xbd7fbbc9,0xbd553d0e,0xbc953d75,0x3cc43d6d,0x3d623cf1,0x3d7bbc48,0x3d22bd46,
0x3d6dbcc4,0x3d22bd46,0x3c48bd7b,0xbc95bd75,0x80003d80,0x3cf13d62,0x3d553d0e,0x3d7f3bc9,0xbcc43d6d,0x3bc93d7f,0x3d0e3d55,0x3d623cf1,0xbd35bd35,0xbd75bc95,0xbd7b3c48,0xbd463d22,
0x3cc43d6d,0x3d463d22,0x3d7b3c48,0x3d75bc95,0xbd800000,0xbd623cf1,0xbd0e3d55,0xbbc93d7f,0xbd6dbcc4,0xbd7f3bc9,0xbd553d0e,0xbcf13d62,0x3d35bd35,0x3c95bd75,0xbc48bd7b,0xbd22bd46,
0xbd353d35,0xbcf13d62,0xbc483d7b,0x3bc93d7f,0x3cc43d6d,0x3d223d46,0x3d553d0e,0x3d753c95,0x8000bd80,0xbc95bd75,0xbd0ebd55,0xbd46bd22,0xbd6dbcc4,0xbd7fbbc9,0xbd7b3c48,0xbd623cf1,
0x3d353d35,0x3d623cf1,0x3d7b3c48,0x3d7fbbc9,0x3d6dbcc4,0x3d46bd22,0x3d0ebd55,0x3c95bd75,0xbd800000,0xbd753c95,0xbd553d0e,0xbd223d46,0xbcc43d6d,0xbbc93d7f,0x3c483d7b,0x3cf13d62,
0x3d6d3cc4,0x3d753c95,0x3d7b3c48,0x3d7f3bc9,0x3d353d35,0x3d463d22,0x3d553d0e,0x3d623cf1,0x3cc43d6d,0x3cf13d62,0x3d0e3d55,0x3d223d46,0x80003d80,0x3bc93d7f,0x3c483d7b,0x3c953d75,
0xbcc43d6d,0xbc953d75,0xbc483d7b,0xbbc93d7f,0xbd353d35,0xbd223d46,0xbd0e3d55,0xbcf13d62,0xbd6d3cc4,0xbd623cf1,0xbd553d0e,0xbd463d22,0xbd800000,0xbd7f3bc9,0xbd7b3c48,0xbd753c95,
0x3d80,0xbc163d7d,0xbc953d75,0xbcdb3d67,0xbd0e3d55,0xbd2c3d3e,0xbd463d22,0xbd5c3d04,0xbd6d3cc4,0xbd783c79,0xbd7f3bc9,0xbd80bb49,0xbd7bbc48,0xbd71bcac,0xbd62bcf1,0xbd4ebd18,
0xbd35bd35,0xbd18bd4e,0xbcf1bd62,0xbcacbd71,0xbc48bd7b,0xbb49bd80,0x3bc9bd7f,0x3c79bd78,0x3cc4bd6d,0x3d04bd5c,0x3d22bd46,0x3d3ebd2c,0x3d55bd0e,0x3d67bcdb,0x3d75bc95,0x3d7dbc16,
0xbd7b3c48,0xbd7dbc16,0xbd62bcf1,0xbd2cbd3e,0x3d80,0xbcac3d71,0xbd223d46,0xbd5c3d04,0x3d55bd0e,0x3d78bc79,0x3d7f3bc9,0x3d673cdb,0xbcc4bd6d,0xbb49bd80,0x3c95bd75,0x3d18bd4e,
0xbd0e3d55,0xbd4e3d18,0xbd753c95,0xbd80bb49,0x3d353d35,0x3cdb3d67,0x3bc93d7f,0xbc793d78,0x3c48bd7b,0x3d04bd5c,0x3d46bd22,0x3d71bcac,0xbd6dbcc4,0xbd3ebd2c,0xbcf1bd62,0xbc16bd7d,
0x3d6dbcc4,0x3d7d3c16,0x3d463d22,0x3cac3d71,0xbc483d7b,0xbd2c3d3e,0xbd753c95,0xbd78bc79,0x3d80,0xbd043d5c,0xbd623cf1,0xbd80bb49,0xbd55bd0e,0xbcdbbd67,0x3bc9bd7f,0x3d18bd4e,
0xbcc43d6d,0xbd4e3d18,0xbd7f3bc9,0xbd67bcdb,0xbd0ebd55,0xbb49bd80,0x3cf1bd62,0x3d5cbd04,0xbd35bd35,0xbc79bd78,0x3c95bd75,0x3d3ebd2c,0x3d7bbc48,0x3d713cac,0x3d223d46,0x3c163d7d,
0xbd0ebd55,0x3c16bd7d,0x3d46bd22,0x3d803b49,0x3cc43d6d,0xbcac3d71,0xbd623cf1,0xbd78bc79,0xbc48bd7b,0x3d04bd5c,0x3d75bc95,0x3d673cdb,0x3d80,0xbd2c3d3e,0xbd7f3bc9,0xbd4ebd18,
0xbd7bbc48,0xbd18bd4e,0x3bc9bd7f,0x3d3ebd2c,0x3d6d3cc4,0x3cdb3d67,0xbc953d75,0xbd5c3d04,0xbd55bd0e,0xbc79bd78,0x3cf1bd62,0x3d71bcac,0x3d353d35,0x3b493d80,0xbd223d46,0xbd7d3c16,
0xbd35bd35,0x3c16bd7d,0x3d62bcf1,0x3d673cdb,0x3c483d7b,0xbd2c3d3e,0xbd7fbbc9,0xbd04bd5c,0x3cc4bd6d,0x3d78bc79,0x3d463d22,0xbb493d80,0xbd553d0e,0xbd71bcac,0xbc95bd75,0x3d18bd4e,
0x3d80,0xbd4e3d18,0xbd75bc95,0xbcacbd71,0x3d0ebd55,0x3d80bb49,0x3d223d46,0xbc793d78,0xbd6d3cc4,0xbd5cbd04,0xbbc9bd7f,0x3d3ebd2c,0x3d7b3c48,0x3cdb3d67,0xbcf13d62,0xbd7d3c16,
0x3d0ebd55,0x3d7d3c16,0x3c953d75,0xbd3e3d2c,0x3d353d35,0xbcac3d71,0xbd7f3bc9,0xbd04bd5c,0xbc483d7b,0xbd783c79,0xbd22bd46,0x3cdbbd67,0xbd6dbcc4,0xbb49bd80,0x3d62bcf1,0x3d4e3d18,
0x3d7bbc48,0x3d183d4e,0xbcf13d62,0xbd80bb49,0x3d80,0xbd673cdb,0xbd46bd22,0x3c79bd78,0xbd553d0e,0xbd5cbd04,0x3bc9bd7f,0x3d71bcac,0xbcc4bd6d,0x3d2cbd3e,0x3d753c95,0x3c163d7d,
0xbcc43d6d,0xbd7dbc16,0xbbc9bd7f,0x3d71bcac,0x3d0e3d55,0xbd2c3d3e,0xbd62bcf1,0x3c79bd78,0xbd35bd35,0x3d04bd5c,0x3d753c95,0xbb493d80,0xbd7b3c48,0xbcdbbd67,0x3d46bd22,0x3d4e3d18,
0x3d6dbcc4,0x3d183d4e,0xbd223d46,0xbd67bcdb,0x3c48bd7b,0x3d80bb49,0x3c953d75,0xbd5c3d04,0x3d80,0xbd783c79,0xbcf1bd62,0x3d3ebd2c,0x3d553d0e,0xbcac3d71,0xbd7fbbc9,0xbc16bd7d,
0x3d7b3c48,0xbc163d7d,0xbd7fbbc9,0x3b49bd80,0x3d6d3cc4,0xbcac3d71,0xbd75bc95,0x3c79bd78,0x3d553d0e,0xbd043d5c,0xbd62bcf1,0x3cdbbd67,0x3d353d35,0xbd2c3d3e,0xbd46bd22,0x3d18bd4e,
0x3d0e3d55,0xbd4e3d18,0xbd22bd46,0x3d3ebd2c,0x3cc43d6d,0xbd673cdb,0xbcf1bd62,0x3d5cbd04,0x3c483d7b,0xbd783c79,0xbc95bd75,0x3d71bcac,0x3d80,0xbd803b49,0xbbc9bd7f,0x3d7dbc16,
0xbd800000,0xbd7dbc16,0xbd75bc95,0xbd67bcdb,0xbd55bd0e,0xbd3ebd2c,0xbd22bd46,0xbd04bd5c,0xbcc4bd6d,0xbc79bd78,0xbbc9bd7f,0x3b49bd80,0x3c48bd7b,0x3cacbd71,0x3cf1bd62,0x3d18bd4e,
0x3d35bd35,0x3d4ebd18,0x3d62bcf1,0x3d71bcac,0x3d7bbc48,0x3d80bb49,0x3d7f3bc9,0x3d783c79,0x3d6d3cc4,0x3d5c3d04,0x3d463d22,0x3d2c3d3e,0x3d0e3d55,0x3cdb3d67,0x3c953d75,0x3c163d7d,
0xbc48bd7b,0x3c16bd7d,0x3cf1bd62,0x3d3ebd2c,0xbd800000,0xbd71bcac,0xbd46bd22,0xbd04bd5c,0x3d0e3d55,0x3c793d78,0xbbc93d7f,0xbcdb3d67,0x3d6dbcc4,0x3d80bb49,0x3d753c95,0x3d4e3d18,
0xbd55bd0e,0xbd18bd4e,0xbc95bd75,0x3b49bd80,0xbd353d35,0xbd673cdb,0xbd7f3bc9,0xbd78bc79,0x3d7b3c48,0x3d5c3d04,0x3d223d46,0x3cac3d71,0x3cc4bd6d,0x3d2cbd3e,0x3d62bcf1,0x3d7dbc16,
0x3cc43d6d,0xbc163d7d,0xbd223d46,0xbd713cac,0xbd7bbc48,0xbd3ebd2c,0xbc95bd75,0x3c79bd78,0xbd800000,0xbd5cbd04,0xbcf1bd62,0x3b49bd80,0x3d0ebd55,0x3d67bcdb,0x3d7f3bc9,0x3d4e3d18,
0xbd6dbcc4,0xbd18bd4e,0xbbc9bd7f,0x3cdbbd67,0x3d55bd0e,0x3d80bb49,0x3d623cf1,0x3d043d5c,0x3d35bd35,0x3d78bc79,0x3d753c95,0x3d2c3d3e,0x3c483d7b,0xbcac3d71,0xbd463d22,0xbd7d3c16,
0x3d55bd0e,0x3d7d3c16,0x3d223d46,0xbb493d80,0xbd6d3cc4,0xbd71bcac,0xbcf1bd62,0x3c79bd78,0x3d7bbc48,0x3d5c3d04,0x3c953d75,0xbcdb3d67,0xbd800000,0xbd3ebd2c,0xbbc9bd7f,0x3d18bd4e,
0x3c48bd7b,0x3d4ebd18,0x3d7f3bc9,0x3d2c3d3e,0xbcc43d6d,0xbd673cdb,0xbd75bc95,0xbd04bd5c,0x3d0ebd55,0x3d78bc79,0x3d623cf1,0x3cac3d71,0xbd353d35,0xbd803b49,0xbd46bd22,0xbc16bd7d,
0x3d35bd35,0x3d7d3c16,0x3cf13d62,0xbcdb3d67,0xbd7b3c48,0xbd3ebd2c,0x3bc9bd7f,0x3d5cbd04,0x3d6d3cc4,0x3c793d78,0xbd223d46,0xbd80bb49,0xbd0ebd55,0x3cacbd71,0x3d75bc95,0x3d4e3d18,
0xbd800000,0xbd18bd4e,0x3c95bd75,0x3d71bcac,0x3d553d0e,0x3b493d80,0xbd463d22,0xbd78bc79,0xbcc4bd6d,0x3d04bd5c,0x3d7fbbc9,0x3d2c3d3e,0xbc483d7b,0xbd673cdb,0xbd62bcf1,0xbc16bd7d,
0x3d553d0e,0xbc163d7d,0xbd753c95,0xbd2cbd3e,0xbd353d35,0xbd71bcac,0xbbc9bd7f,0x3d5cbd04,0xbd7bbc48,0xbc79bd78,0x3d46bd22,0x3d673cdb,0x3cc4bd6d,0x3d80bb49,0x3cf13d62,0xbd183d4e,
0x3c483d7b,0xbd4e3d18,0xbd62bcf1,0x3b49bd80,0xbd800000,0xbcdbbd67,0x3d22bd46,0x3d783c79,0xbd0ebd55,0x3d04bd5c,0x3d7f3bc9,0x3cac3d71,0x3d6dbcc4,0x3d3e3d2c,0xbc953d75,0xbd7d3c16,
0xbd6dbcc4,0x3c16bd7d,0x3d7fbbc9,0x3cac3d71,0xbd553d0e,0xbd3ebd2c,0x3cf1bd62,0x3d783c79,0x3d35bd35,0x3d5c3d04,0xbc953d75,0xbd80bb49,0xbc48bd7b,0x3d67bcdb,0x3d223d46,0xbd183d4e,
0x3cc43d6d,0xbd4e3d18,0xbd46bd22,0x3cdbbd67,0x3d7b3c48,0x3b493d80,0xbd753c95,0xbd04bd5c,0xbd800000,0xbc79bd78,0x3d62bcf1,0x3d2c3d3e,0xbd0e3d55,0xbd71bcac,0x3bc9bd7f,0x3d7dbc16,
0xbc483d7b,0xbd7dbc16,0x3bc9bd7f,0x3d803b49,0xbcc43d6d,0xbd71bcac,0x3c95bd75,0x3d783c79,0xbd0e3d55,0xbd5cbd04,0x3cf1bd62,0x3d673cdb,0xbd353d35,0xbd3ebd2c,0x3d22bd46,0x3d4e3d18,
0xbd553d0e,0xbd18bd4e,0x3d46bd22,0x3d2c3d3e,0xbd6d3cc4,0xbcdbbd67,0x3d62bcf1,0x3d043d5c,0xbd7b3c48,0xbc79bd78,0x3d75bc95,0x3cac3d71,0xbd800000,0xbb49bd80,0x3d7fbbc9,0x3c163d7d,
0x3d80,0xbd7dbc16,0x3c95bd75,0x3d673cdb,0xbd0e3d55,0xbd3ebd2c,0x3d46bd22,0x3d043d5c,0xbd6d3cc4,0xbc79bd78,0x3d7fbbc9,0xbb493d80,0xbd7bbc48,0x3cacbd71,0x3d623cf1,0xbd183d4e,
0xbd35bd35,0x3d4ebd18,0x3cf13d62,0xbd713cac,0xbc48bd7b,0x3d80bb49,0xbbc93d7f,0xbd78bc79,0x3cc4bd6d,0x3d5c3d04,0xbd223d46,0xbd2cbd3e,0x3d55bd0e,0x3cdb3d67,0xbd753c95,0xbc16bd7d,
0xbd7b3c48,0x3c16bd7d,0x3d623cf1,0xbd3e3d2c,0x3d80,0xbd71bcac,0x3d22bd46,0x3d043d5c,0x3d55bd0e,0x3c793d78,0xbd7fbbc9,0x3cdbbd67,0xbcc4bd6d,0x3d80bb49,0xbc953d75,0xbd4ebd18,
0xbd0e3d55,0xbd18bd4e,0x3d75bc95,0xbb493d80,0x3d353d35,0xbd673cdb,0xbbc9bd7f,0x3d783c79,0x3c48bd7b,0x3d5c3d04,0xbd463d22,0xbcacbd71,0xbd6dbcc4,0x3d2cbd3e,0x3cf13d62,0xbd7d3c16,
0x3d6dbcc4,0xbc163d7d,0xbd46bd22,0x3d71bcac,0xbc483d7b,0xbd3ebd2c,0x3d75bc95,0xbc793d78,0x3d80,0xbd5cbd04,0x3d62bcf1,0xbb493d80,0xbd55bd0e,0x3d67bcdb,0xbbc93d7f,0xbd4ebd18,
0xbcc43d6d,0xbd18bd4e,0x3d7fbbc9,0xbcdb3d67,0xbd0ebd55,0x3d80bb49,0xbcf13d62,0xbd04bd5c,0xbd35bd35,0x3d78bc79,0xbc953d75,0xbd2cbd3e,0x3d7bbc48,0xbcac3d71,0xbd22bd46,0x3d7dbc16,
0xbd0ebd55,0x3d7d3c16,0xbd463d22,0x3b49bd80,0x3cc43d6d,0xbd71bcac,0x3d62bcf1,0xbc793d78,0xbc48bd7b,0x3d5c3d04,0xbd753c95,0x3cdbbd67,0x3d80,0xbd3ebd2c,0x3d7fbbc9,0xbd183d4e,
0xbd7bbc48,0x3d4ebd18,0xbbc93d7f,0xbd2cbd3e,0x3d6d3cc4,0xbd673cdb,0x3c95bd75,0x3d043d5c,0xbd55bd0e,0x3d78bc79,0xbcf13d62,0xbcacbd71,0x3d353d35,0xbd803b49,0x3d22bd46,0x3c163d7d,
0xbd35bd35,0x3d7d3c16,0xbd623cf1,0x3cdbbd67,0x3c483d7b,0xbd3ebd2c,0x3d7f3bc9,0xbd5c3d04,0x3cc4bd6d,0x3c793d78,0xbd46bd22,0x3d803b49,0xbd553d0e,0x3cacbd71,0x3c953d75,0xbd4ebd18,
0x3d80,0xbd18bd4e,0x3d753c95,0xbd713cac,0x3d0ebd55,0x3b493d80,0xbd22bd46,0x3d783c79,0xbd6d3cc4,0x3d04bd5c,0x3bc93d7f,0xbd2cbd3e,0x3d7b3c48,0xbd673cdb,0x3cf1bd62,0x3c163d7d,
0x3d0ebd55,0xbc163d7d,0xbc95bd75,0x3d2c3d3e,0x3d353d35,0xbd71bcac,0x3d7fbbc9,0xbd5c3d04,0xbc483d7b,0xbc79bd78,0x3d223d46,0xbd67bcdb,0xbd6dbcc4,0x3d80bb49,0xbd623cf1,0x3d18bd4e,
0x3d7bbc48,0xbd4e3d18,0x3cf1bd62,0xbb493d80,0x3d80,0xbcdbbd67,0x3d463d22,0xbd78bc79,0xbd553d0e,0x3d04bd5c,0xbbc93d7f,0xbcacbd71,0xbcc4bd6d,0x3d3e3d2c,0xbd75bc95,0x3d7dbc16,
0xbcc43d6d,0x3c16bd7d,0x3bc93d7f,0xbcacbd71,0x3d0e3d55,0xbd3ebd2c,0x3d623cf1,0xbd78bc79,0xbd35bd35,0x3d5c3d04,0xbd75bc95,0x3d803b49,0xbd7b3c48,0x3d67bcdb,0xbd463d22,0x3d18bd4e,
0x3d6dbcc4,0xbd4e3d18,0x3d22bd46,0xbcdb3d67,0x3c48bd7b,0x3b493d80,0xbc95bd75,0x3d043d5c,0x3d80,0xbc79bd78,0x3cf13d62,0xbd2cbd3e,0x3d553d0e,0xbd71bcac,0x3d7f3bc9,0xbd7d3c16,
0x3d7b3c48,0xbd7dbc16,0x3d7f3bc9,0xbd80bb49,0x3d6d3cc4,0xbd71bcac,0x3d753c95,0xbd78bc79,0x3d553d0e,0xbd5cbd04,0x3d623cf1,0xbd67bcdb,0x3d353d35,0xbd3ebd2c,0x3d463d22,0xbd4ebd18,
0x3d0e3d55,0xbd18bd4e,0x3d223d46,0xbd2cbd3e,0x3cc43d6d,0xbcdbbd67,0x3cf13d62,0xbd04bd5c,0x3c483d7b,0xbc79bd78,0x3c953d75,0xbcacbd71,0x3d80,0xbb49bd80,0x3bc93d7f,0xbc16bd7d,
0xbd800000,0x3c16bd7d,0x3d753c95,0xbcdb3d67,0xbd55bd0e,0x3d2cbd3e,0x3d223d46,0xbd5c3d04,0xbcc4bd6d,0x3d78bc79,0x3bc93d7f,0xbd80bb49,0x3c48bd7b,0x3d713cac,0xbcf13d62,0xbd4ebd18,
0x3d35bd35,0x3d183d4e,0xbd623cf1,0xbcacbd71,0x3d7bbc48,0x3b493d80,0xbd7fbbc9,0x3c79bd78,0x3d6d3cc4,0xbd043d5c,0xbd46bd22,0x3d3ebd2c,0x3d0e3d55,0xbd673cdb,0xbc95bd75,0x3d7dbc16,
0xbc48bd7b,0x3d7d3c16,0xbcf13d62,0xbd2cbd3e,0xbd800000,0x3cacbd71,0x3d463d22,0xbd5c3d04,0x3d0e3d55,0xbd783c79,0x3bc9bd7f,0x3d673cdb,0x3d6dbcc4,0x3b493d80,0xbd75bc95,0x3d18bd4e,
0xbd55bd0e,0x3d4ebd18,0x3c953d75,0xbd80bb49,0xbd353d35,0xbcdbbd67,0x3d7fbbc9,0xbc793d78,0x3d7b3c48,0xbd043d5c,0xbd22bd46,0x3d71bcac,0x3cc4bd6d,0x3d3e3d2c,0xbd623cf1,0xbc16bd7d,
0x3cc43d6d,0xbd7dbc16,0x3d22bd46,0x3cac3d71,0xbd7bbc48,0x3d2cbd3e,0x3c953d75,0xbd78bc79,0xbd800000,0x3d04bd5c,0x3cf13d62,0xbd80bb49,0x3d0ebd55,0x3cdb3d67,0xbd7fbbc9,0x3d18bd4e,
0xbd6dbcc4,0x3d4ebd18,0x3bc93d7f,0xbd67bcdb,0x3d55bd0e,0x3b493d80,0xbd62bcf1,0x3d5cbd04,0x3d35bd35,0x3c793d78,0xbd75bc95,0x3d3ebd2c,0x3c483d7b,0xbd71bcac,0x3d46bd22,0x3c163d7d,
0x3d55bd0e,0xbc163d7d,0xbd22bd46,0x3d803b49,0xbd6d3cc4,0x3cacbd71,0x3cf13d62,0xbd78bc79,0x3d7bbc48,0xbd043d5c,0xbc95bd75,0x3d673cdb,0xbd800000,0x3d2cbd3e,0x3bc93d7f,0xbd4ebd18,
0x3c48bd7b,0x3d183d4e,0xbd7fbbc9,0x3d3ebd2c,0xbcc43d6d,0xbcdbbd67,0x3d753c95,0xbd5c3d04,0x3d0ebd55,0x3c793d78,0xbd62bcf1,0x3d71bcac,0xbd353d35,0xbb49bd80,0x3d463d22,0xbd7d3c16,
0x3d35bd35,0xbc163d7d,0xbcf1bd62,0x3d673cdb,0xbd7b3c48,0x3d2cbd3e,0xbbc93d7f,0xbd04bd5c,0x3d6d3cc4,0xbd783c79,0x3d22bd46,0xbb493d80,0xbd0ebd55,0x3d713cac,0xbd753c95,0x3d18bd4e,
0xbd800000,0x3d4ebd18,0xbc953d75,0xbcacbd71,0x3d553d0e,0xbd803b49,0x3d46bd22,0xbc793d78,0xbcc4bd6d,0x3d5c3d04,0xbd7f3bc9,0x3d3ebd2c,0xbc483d7b,0xbcdbbd67,0x3d623cf1,0xbd7d3c16,
0x3d553d0e,0xbd7dbc16,0x3d75bc95,0xbd3e3d2c,0xbd353d35,0x3cacbd71,0x3bc93d7f,0xbd04bd5c,0xbd7bbc48,0x3d78bc79,0xbd463d22,0x3cdbbd67,0x3cc4bd6d,0x3b493d80,0xbcf1bd62,0x3d4e3d18,
0x3c483d7b,0xbd18bd4e,0x3d623cf1,0xbd80bb49,0xbd800000,0x3d67bcdb,0xbd223d46,0x3c79bd78,0xbd0ebd55,0x3d5c3d04,0xbd7fbbc9,0x3d71bcac,0x3d6dbcc4,0xbd2c3d3e,0x3c95bd75,0x3c163d7d,
0xbd6dbcc4,0x3d7d3c16,0xbd7f3bc9,0x3d71bcac,0xbd553d0e,0x3d2cbd3e,0xbcf13d62,0x3c79bd78,0x3d35bd35,0xbd043d5c,0x3c95bd75,0xbb493d80,0xbc48bd7b,0x3cdb3d67,0xbd22bd46,0x3d4e3d18,
0x3cc43d6d,0xbd18bd4e,0x3d463d22,0xbd67bcdb,0x3d7b3c48,0xbd803b49,0x3d75bc95,0xbd5c3d04,0xbd800000,0x3d78bc79,0xbd623cf1,0x3d3ebd2c,0xbd0e3d55,0x3cacbd71,0xbbc93d7f,0xbc16bd7d,
0xbc483d7b,0x3c16bd7d,0xbbc93d7f,0x3b49bd80,0xbcc43d6d,0x3cacbd71,0xbc953d75,0x3c79bd78,0xbd0e3d55,0x3d04bd5c,0xbcf13d62,0x3cdbbd67,0xbd353d35,0x3d2cbd3e,0xbd223d46,0x3d18bd4e,
0xbd553d0e,0x3d4ebd18,0xbd463d22,0x3d3ebd2c,0xbd6d3cc4,0x3d67bcdb,0xbd623cf1,0x3d5cbd04,0xbd7b3c48,0x3d78bc79,0xbd753c95,0x3d71bcac,0xbd800000,0x3d80bb49,0xbd7f3bc9,0x3d7dbc16,
0x3d80,0x3c16bd7d,0xbc953d75,0x3cdbbd67,0xbd0e3d55,0x3d2cbd3e,0xbd463d22,0x3d5cbd04,0xbd6d3cc4,0x3d78bc79,0xbd7f3bc9,0x3d803b49,0xbd7bbc48,0x3d713cac,0xbd62bcf1,0x3d4e3d18,
0xbd35bd35,0x3d183d4e,0xbcf1bd62,0x3cac3d71,0xbc48bd7b,0x3b493d80,0x3bc9bd7f,0xbc793d78,0x3cc4bd6d,0xbd043d5c,0x3d22bd46,0xbd3e3d2c,0x3d55bd0e,0xbd673cdb,0x3d75bc95,0xbd7d3c16,
0xbd7b3c48,0x3d7d3c16,0xbd62bcf1,0x3d2c3d3e,0x3d80,0x3cacbd71,0xbd223d46,0x3d5cbd04,0x3d55bd0e,0xbd783c79,0x3d7f3bc9,0xbd67bcdb,0xbcc4bd6d,0x3b493d80,0x3c95bd75,0xbd183d4e,
0xbd0e3d55,0x3d4ebd18,0xbd753c95,0x3d803b49,0x3d353d35,0xbcdbbd67,0x3bc93d7f,0x3c79bd78,0x3c48bd7b,0xbd043d5c,0x3d46bd22,0xbd713cac,0xbd6dbcc4,0x3d3e3d2c,0xbcf1bd62,0x3c163d7d,
0x3d6dbcc4,0xbd7dbc16,0x3d463d22,0xbcacbd71,0xbc483d7b,0x3d2cbd3e,0xbd753c95,0x3d783c79,0x3d80,0x3d04bd5c,0xbd623cf1,0x3d803b49,0xbd55bd0e,0x3cdb3d67,0x3bc9bd7f,0xbd183d4e,
0xbcc43d6d,0x3d4ebd18,0xbd7f3bc9,0x3d673cdb,0xbd0ebd55,0x3b493d80,0x3cf1bd62,0xbd5c3d04,0xbd35bd35,0x3c793d78,0x3c95bd75,0xbd3e3d2c,0x3d7bbc48,0xbd71bcac,0x3d223d46,0xbc16bd7d,
0xbd0ebd55,0xbc163d7d,0x3d46bd22,0xbd80bb49,0x3cc43d6d,0x3cacbd71,0xbd623cf1,0x3d783c79,0xbc48bd7b,0xbd043d5c,0x3d75bc95,0xbd67bcdb,0x3d80,0x3d2cbd3e,0xbd7f3bc9,0x3d4e3d18,
0xbd7bbc48,0x3d183d4e,0x3bc9bd7f,0xbd3e3d2c,0x3d6d3cc4,0xbcdbbd67,0xbc953d75,0x3d5cbd04,0xbd55bd0e,0x3c793d78,0x3cf1bd62,0xbd713cac,0x3d353d35,0xbb49bd80,0xbd223d46,0x3d7dbc16,
0xbd35bd35,0xbc163d7d,0x3d62bcf1,0xbd67bcdb,0x3c483d7b,0x3d2cbd3e,0xbd7fbbc9,0x3d043d5c,0x3cc4bd6d,0xbd783c79,0x3d463d22,0x3b49bd80,0xbd553d0e,0x3d713cac,0xbc95bd75,0xbd183d4e,
0x3d80,0x3d4ebd18,0xbd75bc95,0x3cac3d71,0x3d0ebd55,0xbd803b49,0x3d223d46,0x3c79bd78,0xbd6d3cc4,0x3d5c3d04,0xbbc9bd7f,0xbd3e3d2c,0x3d7b3c48,0xbcdbbd67,0xbcf13d62,0x3d7dbc16,
0x3d0ebd55,0xbd7dbc16,0x3c953d75,0x3d3ebd2c,0x3d353d35,0x3cacbd71,0xbd7f3bc9,0x3d043d5c,0xbc483d7b,0x3d78bc79,0xbd22bd46,0xbcdb3d67,0xbd6dbcc4,0x3b493d80,0x3d62bcf1,0xbd4ebd18,
0x3d7bbc48,0xbd18bd4e,0xbcf13d62,0x3d803b49,0x3d80,0x3d67bcdb,0xbd46bd22,0xbc793d78,0xbd553d0e,0x3d5c3d04,0x3bc9bd7f,0xbd713cac,0xbcc4bd6d,0xbd2c3d3e,0x3d753c95,0xbc16bd7d,
0xbcc43d6d,0x3d7d3c16,0xbbc9bd7f,0xbd713cac,0x3d0e3d55,0x3d2cbd3e,0xbd62bcf1,0xbc793d78,0xbd35bd35,0xbd043d5c,0x3d753c95,0x3b49bd80,0xbd7b3c48,0x3cdb3d67,0x3d46bd22,0xbd4ebd18,
0x3d6dbcc4,0xbd18bd4e,0xbd223d46,0x3d673cdb,0x3c48bd7b,0xbd803b49,0x3c953d75,0x3d5cbd04,0x3d80,0x3d78bc79,0xbcf1bd62,0xbd3e3d2c,0x3d553d0e,0x3cacbd71,0xbd7fbbc9,0x3c163d7d,
0x3d7b3c48,0x3c16bd7d,0xbd7fbbc9,0xbb493d80,0x3d6d3cc4,0x3cacbd71,0xbd75bc95,0xbc793d78,0x3d553d0e,0x3d04bd5c,0xbd62bcf1,0xbcdb3d67,0x3d353d35,0x3d2cbd3e,0xbd46bd22,0xbd183d4e,
0x3d0e3d55,0x3d4ebd18,0xbd22bd46,0xbd3e3d2c,0x3cc43d6d,0x3d67bcdb,0xbcf1bd62,0xbd5c3d04,0x3c483d7b,0x3d78bc79,0xbc95bd75,0xbd713cac,0x3d80,0x3d80bb49,0xbbc9bd7f,0xbd7d3c16,
0xbd800000,0x3d7d3c16,0xbd75bc95,0x3d673cdb,0xbd55bd0e,0x3d3e3d2c,0xbd22bd46,0x3d043d5c,0xbcc4bd6d,0x3c793d78,0xbbc9bd7f,0xbb493d80,0x3c48bd7b,0xbcac3d71,0x3cf1bd62,0xbd183d4e,
0x3d35bd35,0xbd4e3d18,0x3d62bcf1,0xbd713cac,0x3d7bbc48,0xbd803b49,0x3d7f3bc9,0xbd78bc79,0x3d6d3cc4,0xbd5cbd04,0x3d463d22,0xbd2cbd3e,0x3d0e3d55,0xbcdbbd67,0x3c953d75,0xbc16bd7d,
0xbc48bd7b,0xbc163d7d,0x3cf1bd62,0xbd3e3d2c,0xbd800000,0x3d713cac,0xbd46bd22,0x3d043d5c,0x3d0e3d55,0xbc79bd78,0xbbc93d7f,0x3cdbbd67,0x3d6dbcc4,0xbd803b49,0x3d753c95,0xbd4ebd18,
0xbd55bd0e,0x3d183d4e,0xbc95bd75,0xbb493d80,0xbd353d35,0x3d67bcdb,0xbd7f3bc9,0x3d783c79,0x3d7b3c48,0xbd5cbd04,0x3d223d46,0xbcacbd71,0x3cc4bd6d,0xbd2c3d3e,0x3d62bcf1,0xbd7d3c16,
0x3cc43d6d,0x3c16bd7d,0xbd223d46,0x3d71bcac,0xbd7bbc48,0x3d3e3d2c,0xbc95bd75,0xbc793d78,0xbd800000,0x3d5c3d04,0xbcf1bd62,0xbb493d80,0x3d0ebd55,0xbd673cdb,0x3d7f3bc9,0xbd4ebd18,
0xbd6dbcc4,0x3d183d4e,0xbbc9bd7f,0xbcdb3d67,0x3d55bd0e,0xbd803b49,0x3d623cf1,0xbd04bd5c,0x3d35bd35,0xbd783c79,0x3d753c95,0xbd2cbd3e,0x3c483d7b,0x3cacbd71,0xbd463d22,0x3d7dbc16,
0x3d55bd0e,0xbd7dbc16,0x3d223d46,0x3b49bd80,0xbd6d3cc4,0x3d713cac,0xbcf1bd62,0xbc793d78,0x3d7bbc48,0xbd5cbd04,0x3c953d75,0x3cdbbd67,0xbd800000,0x3d3e3d2c,0xbbc9bd7f,0xbd183d4e,
0x3c48bd7b,0xbd4e3d18,0x3d7f3bc9,0xbd2cbd3e,0xbcc43d6d,0x3d67bcdb,0xbd75bc95,0x3d043d5c,0x3d0ebd55,0xbd783c79,0x3d623cf1,0xbcacbd71,0xbd353d35,0x3d80bb49,0xbd46bd22,0x3c163d7d,
0x3d35bd35,0xbd7dbc16,0x3cf13d62,0x3cdbbd67,0xbd7b3c48,0x3d3e3d2c,0x3bc9bd7f,0xbd5c3d04,0x3d6d3cc4,0xbc79bd78,0xbd223d46,0x3d803b49,0xbd0ebd55,0xbcac3d71,0x3d75bc95,0xbd4ebd18,
0xbd800000,0x3d183d4e,0x3c95bd75,0xbd713cac,0x3d553d0e,0xbb49bd80,0xbd463d22,0x3d783c79,0xbcc4bd6d,0xbd043d5c,0x3d7fbbc9,0xbd2cbd3e,0xbc483d7b,0x3d67bcdb,0xbd62bcf1,0x3c163d7d,
0x3d553d0e,0x3c16bd7d,0xbd753c95,0x3d2c3d3e,0xbd353d35,0x3d713cac,0xbbc9bd7f,0xbd5c3d04,0xbd7bbc48,0x3c793d78,0x3d46bd22,0xbd67bcdb,0x3cc4bd6d,0xbd803b49,0x3cf13d62,0x3d18bd4e,
0x3c483d7b,0x3d4ebd18,0xbd62bcf1,0xbb493d80,0xbd800000,0x3cdb3d67,0x3d22bd46,0xbd78bc79,0xbd0ebd55,0xbd043d5c,0x3d7f3bc9,0xbcacbd71,0x3d6dbcc4,0xbd3ebd2c,0xbc953d75,0x3d7dbc16,
0xbd6dbcc4,0xbc163d7d,0x3d7fbbc9,0xbcacbd71,0xbd553d0e,0x3d3e3d2c,0x3cf1bd62,0xbd78bc79,0x3d35bd35,0xbd5cbd04,0xbc953d75,0x3d803b49,0xbc48bd7b,0xbd673cdb,0x3d223d46,0x3d18bd4e,
0x3cc43d6d,0x3d4ebd18,0xbd46bd22,0xbcdb3d67,0x3d7b3c48,0xbb49bd80,0xbd753c95,0x3d043d5c,0xbd800000,0x3c793d78,0x3d62bcf1,0xbd2cbd3e,0xbd0e3d55,0x3d713cac,0x3bc9bd7f,0xbd7d3c16,
0xbc483d7b,0x3d7d3c16,0x3bc9bd7f,0xbd80bb49,0xbcc43d6d,0x3d713cac,0x3c95bd75,0xbd78bc79,0xbd0e3d55,0x3d5c3d04,0x3cf1bd62,0xbd67bcdb,0xbd353d35,0x3d3e3d2c,0x3d22bd46,0xbd4ebd18,
0xbd553d0e,0x3d183d4e,0x3d46bd22,0xbd2cbd3e,0xbd6d3cc4,0x3cdb3d67,0x3d62bcf1,0xbd04bd5c,0xbd7b3c48,0x3c793d78,0x3d75bc95,0xbcacbd71,0xbd800000,0x3b493d80,0x3d7fbbc9,0xbc16bd7d,
0x3d80,0x3d7d3c16,0x3c95bd75,0xbd67bcdb,0xbd0e3d55,0x3d3e3d2c,0x3d46bd22,0xbd04bd5c,0xbd6d3cc4,0x3c793d78,0x3d7fbbc9,0x3b49bd80,0xbd7bbc48,0xbcac3d71,0x3d623cf1,0x3d18bd4e,
0xbd35bd35,0xbd4e3d18,0x3cf13d62,0x3d71bcac,0xbc48bd7b,0xbd803b49,0xbbc93d7f,0x3d783c79,0x3cc4bd6d,0xbd5cbd04,0xbd223d46,0x3d2c3d3e,0x3d55bd0e,0xbcdbbd67,0xbd753c95,0x3c163d7d,
0xbd7b3c48,0xbc163d7d,0x3d623cf1,0x3d3ebd2c,0x3d80,0x3d713cac,0x3d22bd46,0xbd04bd5c,0x3d55bd0e,0xbc79bd78,0xbd7fbbc9,0xbcdb3d67,0xbcc4bd6d,0xbd803b49,0xbc953d75,0x3d4e3d18,
0xbd0e3d55,0x3d183d4e,0x3d75bc95,0x3b49bd80,0x3d353d35,0x3d67bcdb,0xbbc9bd7f,0xbd78bc79,0x3c48bd7b,0xbd5cbd04,0xbd463d22,0x3cac3d71,0xbd6dbcc4,0xbd2c3d3e,0x3cf13d62,0x3d7dbc16,
0x3d6dbcc4,0x3c16bd7d,0xbd46bd22,0xbd713cac,0xbc483d7b,0x3d3e3d2c,0x3d75bc95,0x3c79bd78,0x3d80,0x3d5c3d04,0x3d62bcf1,0x3b49bd80,0xbd55bd0e,0xbd673cdb,0xbbc93d7f,0x3d4e3d18,
0xbcc43d6d,0x3d183d4e,0x3d7fbbc9,0x3cdbbd67,0xbd0ebd55,0xbd803b49,0xbcf13d62,0x3d043d5c,0xbd35bd35,0xbd783c79,0xbc953d75,0x3d2c3d3e,0x3d7bbc48,0x3cacbd71,0xbd22bd46,0xbd7d3c16,
0xbd0ebd55,0xbd7dbc16,0xbd463d22,0xbb493d80,0x3cc43d6d,0x3d713cac,0x3d62bcf1,0x3c79bd78,0xbc48bd7b,0xbd5cbd04,0xbd753c95,0xbcdb3d67,0x3d80,0x3d3e3d2c,0x3d7fbbc9,0x3d18bd4e,
0xbd7bbc48,0xbd4e3d18,0xbbc93d7f,0x3d2c3d3e,0x3d6d3cc4,0x3d67bcdb,0x3c95bd75,0xbd04bd5c,0xbd55bd0e,0xbd783c79,0xbcf13d62,0x3cac3d71,0x3d353d35,0x3d80bb49,0x3d22bd46,0xbc16bd7d,
0xbd35bd35,0xbd7dbc16,0xbd623cf1,0xbcdb3d67,0x3c483d7b,0x3d3e3d2c,0x3d7f3bc9,0x3d5cbd04,0x3cc4bd6d,0xbc79bd78,0xbd46bd22,0xbd80bb49,0xbd553d0e,0xbcac3d71,0x3c953d75,0x3d4e3d18,
0x3d80,0x3d183d4e,0x3d753c95,0x3d71bcac,0x3d0ebd55,0xbb49bd80,0xbd22bd46,0xbd78bc79,0xbd6d3cc4,0xbd043d5c,0x3bc93d7f,0x3d2c3d3e,0x3d7b3c48,0x3d67bcdb,0x3cf1bd62,0xbc16bd7d,
0x3d0ebd55,0x3c16bd7d,0xbc95bd75,0xbd2cbd3e,0x3d353d35,0x3d713cac,0x3d7fbbc9,0x3d5cbd04,0xbc483d7b,0x3c793d78,0x3d223d46,0x3d673cdb,0xbd6dbcc4,0xbd803b49,0xbd623cf1,0xbd183d4e,
0x3d7bbc48,0x3d4ebd18,0x3cf1bd62,0x3b49bd80,0x3d80,0x3cdb3d67,0x3d463d22,0x3d783c79,0xbd553d0e,0xbd043d5c,0xbbc93d7f,0x3cac3d71,0xbcc4bd6d,0xbd3ebd2c,0xbd75bc95,0xbd7d3c16,
0xbcc43d6d,0xbc163d7d,0x3bc93d7f,0x3cac3d71,0x3d0e3d55,0x3d3e3d2c,0x3d623cf1,0x3d783c79,0xbd35bd35,0xbd5cbd04,0xbd75bc95,0xbd80bb49,0xbd7b3c48,0xbd673cdb,0xbd463d22,0xbd183d4e,
0x3d6dbcc4,0x3d4ebd18,0x3d22bd46,0x3cdbbd67,0x3c48bd7b,0xbb49bd80,0xbc95bd75,0xbd04bd5c,0x3d80,0x3c793d78,0x3cf13d62,0x3d2c3d3e,0x3d553d0e,0x3d713cac,0x3d7f3bc9,0x3d7dbc16,
0x3d7b3c48,0x3d7d3c16,0x3d7f3bc9,0x3d803b49,0x3d6d3cc4,0x3d713cac,0x3d753c95,0x3d783c79,0x3d553d0e,0x3d5c3d04,0x3d623cf1,0x3d673cdb,0x3d353d35,0x3d3e3d2c,0x3d463d22,0x3d4e3d18,
0x3d0e3d55,0x3d183d4e,0x3d223d46,0x3d2c3d3e,0x3cc43d6d,0x3cdb3d67,0x3cf13d62,0x3d043d5c,0x3c483d7b,0x3c793d78,0x3c953d75,0x3cac3d71,0x3d80,0x3b493d80,0x3bc93d7f,0x3c163d7d,
0xbd800000,0xbc163d7d,0x3d753c95,0x3cdbbd67,0xbd55bd0e,0xbd2c3d3e,0x3d223d46,0x3d5cbd04,0xbcc4bd6d,0xbd783c79,0x3bc93d7f,0x3d803b49,0x3c48bd7b,0xbd71bcac,0xbcf13d62,0x3d4e3d18,
0x3d35bd35,0xbd18bd4e,0xbd623cf1,0x3cac3d71,0x3d7bbc48,0xbb49bd80,0xbd7fbbc9,0xbc793d78,0x3d6d3cc4,0x3d04bd5c,0xbd46bd22,0xbd3e3d2c,0x3d0e3d55,0x3d67bcdb,0xbc95bd75,0xbd7d3c16,
0xbc48bd7b,0xbd7dbc16,0xbcf13d62,0x3d2c3d3e,0xbd800000,0xbcac3d71,0x3d463d22,0x3d5cbd04,0x3d0e3d55,0x3d78bc79,0x3bc9bd7f,0xbd67bcdb,0x3d6dbcc4,0xbb49bd80,0xbd75bc95,0xbd183d4e,
0xbd55bd0e,0xbd4e3d18,0x3c953d75,0x3d803b49,0xbd353d35,0x3cdb3d67,0x3d7fbbc9,0x3c79bd78,0x3d7b3c48,0x3d04bd5c,0xbd22bd46,0xbd713cac,0x3cc4bd6d,0xbd3ebd2c,0xbd623cf1,0x3c163d7d,
0x3cc43d6d,0x3d7d3c16,0x3d22bd46,0xbcacbd71,0xbd7bbc48,0xbd2c3d3e,0x3c953d75,0x3d783c79,0xbd800000,0xbd043d5c,0x3cf13d62,0x3d803b49,0x3d0ebd55,0xbcdbbd67,0xbd7fbbc9,0xbd183d4e,
0xbd6dbcc4,0xbd4e3d18,0x3bc93d7f,0x3d673cdb,0x3d55bd0e,0xbb49bd80,0xbd62bcf1,0xbd5c3d04,0x3d35bd35,0xbc79bd78,0xbd75bc95,0xbd3e3d2c,0x3c483d7b,0x3d713cac,0x3d46bd22,0xbc16bd7d,
0x3d55bd0e,0x3c16bd7d,0xbd22bd46,0xbd80bb49,0xbd6d3cc4,0xbcac3d71,0x3cf13d62,0x3d783c79,0x3d7bbc48,0x3d04bd5c,0xbc95bd75,0xbd67bcdb,0xbd800000,0xbd2c3d3e,0x3bc93d7f,0x3d4e3d18,
0x3c48bd7b,0xbd18bd4e,0xbd7fbbc9,0xbd3e3d2c,0xbcc43d6d,0x3cdb3d67,0x3d753c95,0x3d5cbd04,0x3d0ebd55,0xbc79bd78,0xbd62bcf1,0xbd713cac,0xbd353d35,0x3b493d80,0x3d463d22,0x3d7dbc16,
0x3d35bd35,0x3c16bd7d,0xbcf1bd62,0xbd67bcdb,0xbd7b3c48,0xbd2c3d3e,0xbbc93d7f,0x3d043d5c,0x3d6d3cc4,0x3d78bc79,0x3d22bd46,0x3b49bd80,0xbd0ebd55,0xbd71bcac,0xbd753c95,0xbd183d4e,
0xbd800000,0xbd4e3d18,0xbc953d75,0x3cac3d71,0x3d553d0e,0x3d80bb49,0x3d46bd22,0x3c79bd78,0xbcc4bd6d,0xbd5cbd04,0xbd7f3bc9,0xbd3e3d2c,0xbc483d7b,0x3cdb3d67,0x3d623cf1,0x3d7dbc16,
0x3d553d0e,0x3d7d3c16,0x3d75bc95,0x3d3ebd2c,0xbd353d35,0xbcac3d71,0x3bc93d7f,0x3d043d5c,0xbd7bbc48,0xbd783c79,0xbd463d22,0xbcdb3d67,0x3cc4bd6d,0xbb49bd80,0xbcf1bd62,0xbd4ebd18,
0x3c483d7b,0x3d183d4e,0x3d623cf1,0x3d803b49,0xbd800000,0xbd673cdb,0xbd223d46,0xbc793d78,0xbd0ebd55,0xbd5cbd04,0xbd7fbbc9,0xbd713cac,0x3d6dbcc4,0x3d2cbd3e,0x3c95bd75,0xbc16bd7d,
0xbd6dbcc4,0xbd7dbc16,0xbd7f3bc9,0xbd713cac,0xbd553d0e,0xbd2c3d3e,0xbcf13d62,0xbc793d78,0x3d35bd35,0x3d04bd5c,0x3c95bd75,0x3b49bd80,0xbc48bd7b,0xbcdbbd67,0xbd22bd46,0xbd4ebd18,
0x3cc43d6d,0x3d183d4e,0x3d463d22,0x3d673cdb,0x3d7b3c48,0x3d80bb49,0x3d75bc95,0x3d5cbd04,0xbd800000,0xbd783c79,0xbd623cf1,0xbd3e3d2c,0xbd0e3d55,0xbcac3d71,0xbbc93d7f,0x3c163d7d,
0xbc483d7b,0xbc163d7d,0xbbc93d7f,0xbb493d80,0xbcc43d6d,0xbcac3d71,0xbc953d75,0xbc793d78,0xbd0e3d55,0xbd043d5c,0xbcf13d62,0xbcdb3d67,0xbd353d35,0xbd2c3d3e,0xbd223d46,0xbd183d4e,
0xbd553d0e,0xbd4e3d18,0xbd463d22,0xbd3e3d2c,0xbd6d3cc4,0xbd673cdb,0xbd623cf1,0xbd5c3d04,0xbd7b3c48,0xbd783c79,0xbd753c95,0xbd713cac,0xbd800000,0xbd803b49,0xbd7f3bc9,0xbd7d3c16,
0x3f003f00,0xbf003f00,0x3f003f00,0xbf003f00,0x3f003f00,0xbf003f00,0x3f003f00,0xbf003f00,0x3f003f00,0xbf003f00,0x3f003f00,0xbf003f00,0x3f003f00,0xbf003f00,0x3f003f00,0xbf003f00,
0x3eff3f00,0xbd490000,0x3ea23eb5,0xbec6beb5,0x3ef53efb,0xbe15bdc8,0x3e713e8e,0xbee2bed5,0x3ee23eed,0xbe71be44,0x3e153e44,0xbef5beed,0x3ec63ed5,0xbea2be8e,0x3d493dc8,0xbeffbefb,
0x3efb3f00,0xbdc80000,0xbdc80000,0xbefbbf00,0x3ed53eed,0xbe8ebe44,0xbe8ebe44,0xbed5beed,0x3e8e3eb5,0xbed5beb5,0xbed5beb5,0xbe8ebeb5,0x3dc83e44,0xbefbbeed,0xbefbbeed,0xbdc8be44,
0x3ef53f00,0xbe150000,0xbee2beb5,0xbe71beb5,0x3ea23ed5,0xbec6be8e,0xbeffbefb,0x3d49bdc8,0x3d493e44,0xbeffbeed,0xbec6beed,0x3ea23e44,0xbe71bdc8,0xbee2befb,0xbe15be8e,0x3ef53ed5,
0x3eed3f00,0xbe440000,0xbeedbf00,0x3e440000,0x3e443eb5,0xbeedbeb5,0xbe44beb5,0x3eed3eb5,0xbe440000,0xbeedbf00,0x3e440000,0x3eed3f00,0xbeedbeb5,0xbe44beb5,0x3eed3eb5,0x3e443eb5,
0x3ee23f00,0xbe710000,0xbe15beb5,0x3ef53eb5,0x3d493e8e,0xbeffbed5,0x3ea23dc8,0x3ec63efb,0xbec6be44,0xbea2beed,0x3eff3eed,0xbd493e44,0xbef5befb,0x3e15bdc8,0x3e713ed5,0xbee2be8e,
0x3ed53f00,0xbe8e0000,0x3e8e0000,0x3ed53f00,0xbdc83e44,0xbefbbeed,0x3efb3eed,0xbdc83e44,0xbefbbeb5,0xbdc8beb5,0x3dc83eb5,0xbefbbeb5,0xbe8ebeed,0x3ed53e44,0xbed5be44,0xbe8ebeed,
0x3ec63f00,0xbea20000,0x3eff3eb5,0x3d493eb5,0xbe713dc8,0xbee2befb,0x3e153ed5,0xbef5be8e,0xbef5beed,0x3e15be44,0xbee2be44,0xbe71beed,0x3d49be8e,0x3eff3ed5,0xbea2befb,0x3ec63dc8,
0x3f00,0xbf000000,0x3f00,0xbf000000,0xbf00,0x3f000000,0xbf00,0x3f000000,0x3f00,0xbf000000,0x3f00,0xbf000000,0xbf00,0x3f000000,0xbf00,0x3f000000,
0xbd493f00,0xbeff0000,0xbec63eb5,0xbea2beb5,0x3e15befb,0x3ef53dc8,0x3ee2be8e,0x3e713ed5,0xbe713eed,0xbee2be44,0xbef53e44,0xbe15beed,0x3ea2bed5,0x3ec63e8e,0x3effbdc8,0x3d493efb,
0xbdc83f00,0xbefb0000,0xbefb0000,0x3dc8bf00,0x3e8ebeed,0x3ed53e44,0x3ed53e44,0xbe8e3eed,0xbed53eb5,0xbe8ebeb5,0xbe8ebeb5,0x3ed5beb5,0x3efbbe44,0x3dc83eed,0x3dc83eed,0xbefb3e44,
0xbe153f00,0xbef50000,0xbe71beb5,0x3ee2beb5,0x3ec6bed5,0x3ea23e8e,0xbd493efb,0xbeff3dc8,0xbeff3e44,0xbd49beed,0x3ea2beed,0x3ec63e44,0x3ee23dc8,0xbe713efb,0xbef53e8e,0xbe15bed5,
0xbe443f00,0xbeed0000,0x3e44bf00,0x3eed0000,0x3eedbeb5,0x3e443eb5,0xbeed3eb5,0xbe44beb5,0xbeed0000,0x3e44bf00,0x3eed0000,0xbe443f00,0x3e443eb5,0xbeed3eb5,0xbe44beb5,0x3eedbeb5,
0xbe713f00,0xbee20000,0x3ef5beb5,0x3e153eb5,0x3effbe8e,0x3d493ed5,0xbec6bdc8,0x3ea2befb,0xbea2be44,0x3ec6beed,0xbd493eed,0xbeff3e44,0xbe153efb,0xbef53dc8,0x3ee2bed5,0x3e713e8e,
0xbe8e3f00,0xbed50000,0x3ed50000,0xbe8e3f00,0x3efbbe44,0xbdc83eed,0x3dc8beed,0x3efbbe44,0xbdc8beb5,0x3efbbeb5,0xbefb3eb5,0xbdc8beb5,0xbed53eed,0xbe8ebe44,0x3e8e3e44,0xbed53eed,
0xbea23f00,0xbec60000,0x3d493eb5,0xbeff3eb5,0x3ee2bdc8,0xbe713efb,0x3ef5bed5,0x3e153e8e,0x3e15beed,0x3ef5be44,0xbe71be44,0x3ee2beed,0xbeff3e8e,0x3d49bed5,0xbec63efb,0xbea2bdc8,
0x3eb53f00,0xbeb50000,0x3eb53f00,0xbeb50000,0xbeb50000,0xbeb5bf00,0xbeb50000,0xbeb5bf00,0xbeb5bf00,0x3eb50000,0xbeb5bf00,0x3eb50000,0x3eb50000,0x3eb53f00,0x3eb50000,0x3eb53f00,
0xbeff3f00,0x3d490000,0xbea23eb5,0x3ec6beb5,0xbef53efb,0x3e15bdc8,0xbe713e8e,0x3ee2bed5,0xbee23eed,0x3e71be44,0xbe153e44,0x3ef5beed,0xbec63ed5,0x3ea2be8e,0xbd493dc8,0x3effbefb,
0xbefb3f00,0x3dc80000,0x3dc80000,0x3efbbf00,0xbed53eed,0x3e8ebe44,0x3e8ebe44,0x3ed5beed,0xbe8e3eb5,0x3ed5beb5,0x3ed5beb5,0x3e8ebeb5,0xbdc83e44,0x3efbbeed,0x3efbbeed,0x3dc8be44,
0xbef53f00,0x3e150000,0x3ee2beb5,0x3e71beb5,0xbea23ed5,0x3ec6be8e,0x3effbefb,0xbd49bdc8,0xbd493e44,0x3effbeed,0x3ec6beed,0xbea23e44,0x3e71bdc8,0x3ee2befb,0x3e15be8e,0xbef53ed5,
0xbeed3f00,0x3e440000,0x3eedbf00,0xbe440000,0xbe443eb5,0x3eedbeb5,0x3e44beb5,0xbeed3eb5,0x3e440000,0x3eedbf00,0xbe440000,0xbeed3f00,0x3eedbeb5,0x3e44beb5,0xbeed3eb5,0xbe443eb5,
0xbee23f00,0x3e710000,0x3e15beb5,0xbef53eb5,0xbd493e8e,0x3effbed5,0xbea23dc8,0xbec63efb,0x3ec6be44,0x3ea2beed,0xbeff3eed,0x3d493e44,0x3ef5befb,0xbe15bdc8,0xbe713ed5,0x3ee2be8e,
0xbed53f00,0x3e8e0000,0xbe8e0000,0xbed53f00,0x3dc83e44,0x3efbbeed,0xbefb3eed,0x3dc83e44,0x3efbbeb5,0x3dc8beb5,0xbdc83eb5,0x3efbbeb5,0x3e8ebeed,0xbed53e44,0x3ed5be44,0x3e8ebeed,
0xbec63f00,0x3ea20000,0xbeff3eb5,0xbd493eb5,0x3e713dc8,0x3ee2befb,0xbe153ed5,0x3ef5be8e,0x3ef5beed,0xbe15be44,0x3ee2be44,0x3e71beed,0xbd49be8e,0xbeff3ed5,0x3ea2befb,0xbec63dc8,
0xbeb53f00,0xbeb50000,0xbeb53f00,0xbeb50000,0x3eb50000,0xbeb53f00,0x3eb50000,0xbeb53f00,0x3eb5bf00,0x3eb50000,0x3eb5bf00,0x3eb50000,0xbeb50000,0x3eb5bf00,0xbeb50000,0x3eb5bf00,
0x3d493f00,0x3eff0000,0x3ec63eb5,0x3ea2beb5,0xbe15befb,0xbef53dc8,0xbee2be8e,0xbe713ed5,0x3e713eed,0x3ee2be44,0x3ef53e44,0x3e15beed,0xbea2bed5,0xbec63e8e,0xbeffbdc8,0xbd493efb,
0x3dc83f00,0x3efb0000,0x3efb0000,0xbdc8bf00,0xbe8ebeed,0xbed53e44,0xbed53e44,0x3e8e3eed,0x3ed53eb5,0x3e8ebeb5,0x3e8ebeb5,0xbed5beb5,0xbefbbe44,0xbdc83eed,0xbdc83eed,0x3efb3e44,
0x3e153f00,0x3ef50000,0x3e71beb5,0xbee2beb5,0xbec6bed5,0xbea23e8e,0x3d493efb,0x3eff3dc8,0x3eff3e44,0x3d49beed,0xbea2beed,0xbec63e44,0xbee23dc8,0x3e713efb,0x3ef53e8e,0x3e15bed5,
0x3e443f00,0x3eed0000,0xbe44bf00,0xbeed0000,0xbeedbeb5,0xbe443eb5,0x3eed3eb5,0x3e44beb5,0x3eed0000,0xbe44bf00,0xbeed0000,0x3e443f00,0xbe443eb5,0x3eed3eb5,0x3e44beb5,0xbeedbeb5,
0x3e713f00,0x3ee20000,0xbef5beb5,0xbe153eb5,0xbeffbe8e,0xbd493ed5,0x3ec6bdc8,0xbea2befb,0x3ea2be44,0xbec6beed,0x3d493eed,0x3eff3e44,0x3e153efb,0x3ef53dc8,0xbee2bed5,0xbe713e8e,
0x3e8e3f00,0x3ed50000,0xbed50000,0x3e8e3f00,0xbefbbe44,0x3dc83eed,0xbdc8beed,0xbefbbe44,0x3dc8beb5,0xbefbbeb5,0x3efb3eb5,0x3dc8beb5,0x3ed53eed,0x3e8ebe44,0xbe8e3e44,0x3ed53eed,
0x3ea23f00,0x3ec60000,0xbd493eb5,0x3eff3eb5,0xbee2bdc8,0x3e713efb,0xbef5bed5,0xbe153e8e,0xbe15beed,0xbef5be44,0x3e71be44,0xbee2beed,0x3eff3e8e,0xbd49bed5,0x3ec63efb,0x3ea2bdc8,
0x3f003f00,0xbf003f00,0x3f003f00,0xbf003f00,0x3f003f00,0xbf003f00,0x3f003f00,0xbf003f00,0x3f003f00,0xbf003f00,0x3f003f00,0xbf003f00,0x3f003f00,0xbf003f00,0x3f003f00,0xbf003f00,
0xbd490000,0xbeffbf00,0xbec6beb5,0xbea2beb5,0xbe15bdc8,0xbef5befb,0xbee2bed5,0xbe71be8e,0xbe71be44,0xbee2beed,0xbef5beed,0xbe15be44,0xbea2be8e,0xbec6bed5,0xbeffbefb,0xbd49bdc8,
0xbefbbf00,0x3dc80000,0x3dc80000,0x3efb3f00,0xbed5beed,0x3e8e3e44,0x3e8e3e44,0x3ed53eed,0xbe8ebeb5,0x3ed53eb5,0x3ed53eb5,0x3e8e3eb5,0xbdc8be44,0x3efb3eed,0x3efb3eed,0x3dc83e44,
0x3e150000,0x3ef53f00,0x3e713eb5,0xbee2beb5,0x3ec63e8e,0x3ea23ed5,0xbd493dc8,0xbeffbefb,0x3eff3eed,0x3d493e44,0xbea2be44,0xbec6beed,0x3ee23efb,0xbe71bdc8,0xbef5bed5,0xbe15be8e,
0x3eed3f00,0xbe440000,0xbeedbf00,0x3e440000,0x3e443eb5,0xbeedbeb5,0xbe44beb5,0x3eed3eb5,0xbe440000,0xbeedbf00,0x3e440000,0x3eed3f00,0xbeedbeb5,0xbe44beb5,0x3eed3eb5,0x3e443eb5,
0xbe710000,0xbee2bf00,0x3ef53eb5,0x3e153eb5,0xbeffbed5,0xbd49be8e,0x3ec63efb,0xbea2bdc8,0xbea2beed,0x3ec63e44,0xbd493e44,0xbeffbeed,0x3e15bdc8,0x3ef53efb,0xbee2be8e,0xbe71bed5,
0xbed5bf00,0x3e8e0000,0xbe8e0000,0xbed5bf00,0x3dc8be44,0x3efb3eed,0xbefbbeed,0x3dc8be44,0x3efb3eb5,0x3dc83eb5,0xbdc8beb5,0x3efb3eb5,0x3e8e3eed,0xbed5be44,0x3ed53e44,0x3e8e3eed,
0x3ea20000,0x3ec63f00,0xbd49beb5,0x3eff3eb5,0x3ee23efb,0xbe713dc8,0x3ef53e8e,0x3e153ed5,0xbe153e44,0xbef5beed,0x3e713eed,0xbee2be44,0xbeffbed5,0x3d49be8e,0xbec6bdc8,0xbea2befb,
0x3f00,0xbf000000,0x3f00,0xbf000000,0xbf00,0x3f000000,0xbf00,0x3f000000,0x3f00,0xbf000000,0x3f00,0xbf000000,0xbf00,0x3f000000,0xbf00,0x3f000000,
0xbeff0000,0x3d49bf00,0xbea2beb5,0x3ec6beb5,0x3ef53dc8,0xbe153efb,0x3e713ed5,0xbee23e8e,0xbee2be44,0x3e71beed,0xbe15beed,0x3ef5be44,0x3ec63e8e,0xbea23ed5,0x3d493efb,0xbeff3dc8,
0x3dc8bf00,0x3efb0000,0x3efb0000,0xbdc83f00,0xbe8e3eed,0xbed5be44,0xbed5be44,0x3e8ebeed,0x3ed5beb5,0x3e8e3eb5,0x3e8e3eb5,0xbed53eb5,0xbefb3e44,0xbdc8beed,0xbdc8beed,0x3efbbe44,
0x3ef50000,0xbe153f00,0xbee23eb5,0xbe71beb5,0xbea2be8e,0x3ec6bed5,0x3effbdc8,0xbd493efb,0x3d493eed,0xbeff3e44,0xbec6be44,0x3ea2beed,0x3e71befb,0x3ee23dc8,0x3e153ed5,0xbef53e8e,
0xbe443f00,0xbeed0000,0x3e44bf00,0x3eed0000,0x3eedbeb5,0x3e443eb5,0xbeed3eb5,0xbe44beb5,0xbeed0000,0x3e44bf00,0x3eed0000,0xbe443f00,0x3e443eb5,0xbeed3eb5,0xbe44beb5,0x3eedbeb5,
0xbee20000,0x3e71bf00,0x3e153eb5,0xbef53eb5,0x3d493ed5,0xbeff3e8e,0x3ea2befb,0x3ec63dc8,0x3ec6beed,0x3ea23e44,0xbeff3e44,0x3d49beed,0xbef53dc8,0x3e15befb,0x3e713e8e,0xbee23ed5,
0x3e8ebf00,0x3ed50000,0xbed50000,0x3e8ebf00,0xbefb3e44,0x3dc8beed,0xbdc83eed,0xbefb3e44,0x3dc83eb5,0xbefb3eb5,0x3efbbeb5,0x3dc83eb5,0x3ed5beed,0x3e8e3e44,0xbe8ebe44,0x3ed5beed,
0x3ec60000,0xbea23f00,0x3effbeb5,0x3d493eb5,0x3e71befb,0x3ee2bdc8,0xbe15be8e,0x3ef5bed5,0xbef53e44,0x3e15beed,0xbee23eed,0xbe71be44,0xbd493ed5,0xbeff3e8e,0x3ea23dc8,0xbec63efb,
0x3eb53f00,0xbeb50000,0x3eb53f00,0xbeb50000,0xbeb50000,0xbeb5bf00,0xbeb50000,0xbeb5bf00,0xbeb5bf00,0x3eb50000,0xbeb5bf00,0x3eb50000,0x3eb50000,0x3eb53f00,0x3eb50000,0x3eb53f00,
0x3d490000,0x3effbf00,0x3ec6beb5,0x3ea2beb5,0x3e15bdc8,0x3ef5befb,0x3ee2bed5,0x3e71be8e,0x3e71be44,0x3ee2beed,0x3ef5beed,0x3e15be44,0x3ea2be8e,0x3ec6bed5,0x3effbefb,0x3d49bdc8,
0x3efbbf00,0xbdc80000,0xbdc80000,0xbefb3f00,0x3ed5beed,0xbe8e3e44,0xbe8e3e44,0xbed53eed,0x3e8ebeb5,0xbed53eb5,0xbed53eb5,0xbe8e3eb5,0x3dc8be44,0xbefb3eed,0xbefb3eed,0xbdc83e44,
0xbe150000,0xbef53f00,0xbe713eb5,0x3ee2beb5,0xbec63e8e,0xbea23ed5,0x3d493dc8,0x3effbefb,0xbeff3eed,0xbd493e44,0x3ea2be44,0x3ec6beed,0xbee23efb,0x3e71bdc8,0x3ef5bed5,0x3e15be8e,
0xbeed3f00,0x3e440000,0x3eedbf00,0xbe440000,0xbe443eb5,0x3eedbeb5,0x3e44beb5,0xbeed3eb5,0x3e440000,0x3eedbf00,0xbe440000,0xbeed3f00,0x3eedbeb5,0x3e44beb5,0xbeed3eb5,0xbe443eb5,
0x3e710000,0x3ee2bf00,0xbef53eb5,0xbe153eb5,0x3effbed5,0x3d49be8e,0xbec63efb,0x3ea2bdc8,0x3ea2beed,0xbec63e44,0x3d493e44,0x3effbeed,0xbe15bdc8,0xbef53efb,0x3ee2be8e,0x3e71bed5,
0x3ed5bf00,0xbe8e0000,0x3e8e0000,0x3ed5bf00,0xbdc8be44,0xbefb3eed,0x3efbbeed,0xbdc8be44,0xbefb3eb5,0xbdc83eb5,0x3dc8beb5,0xbefb3eb5,0xbe8e3eed,0x3ed5be44,0xbed53e44,0xbe8e3eed,
0xbea20000,0xbec63f00,0x3d49beb5,0xbeff3eb5,0xbee23efb,0x3e713dc8,0xbef53e8e,0xbe153ed5,0x3e153e44,0x3ef5beed,0xbe713eed,0x3ee2be44,0x3effbed5,0xbd49be8e,0x3ec6bdc8,0x3ea2befb,
0xbeb53f00,0xbeb50000,0xbeb53f00,0xbeb50000,0x3eb50000,0xbeb53f00,0x3eb50000,0xbeb53f00,0x3eb5bf00,0x3eb50000,0x3eb5bf00,0x3eb50000,0xbeb50000,0x3eb5bf00,0xbeb50000,0x3eb5bf00,
0x3eff0000,0xbd49bf00,0x3ea2beb5,0xbec6beb5,0xbef53dc8,0x3e153efb,0xbe713ed5,0x3ee23e8e,0x3ee2be44,0xbe71beed,0x3e15beed,0xbef5be44,0xbec63e8e,0x3ea23ed5,0xbd493efb,0x3eff3dc8,
0xbdc8bf00,0xbefb0000,0xbefb0000,0x3dc83f00,0x3e8e3eed,0x3ed5be44,0x3ed5be44,0xbe8ebeed,0xbed5beb5,0xbe8e3eb5,0xbe8e3eb5,0x3ed53eb5,0x3efb3e44,0x3dc8beed,0x3dc8beed,0xbefbbe44,
0xbef50000,0x3e153f00,0x3ee23eb5,0x3e71beb5,0x3ea2be8e,0xbec6bed5,0xbeffbdc8,0x3d493efb,0xbd493eed,0x3eff3e44,0x3ec6be44,0xbea2beed,0xbe71befb,0xbee23dc8,0xbe153ed5,0x3ef53e8e,
0x3e443f00,0x3eed0000,0xbe44bf00,0xbeed0000,0xbeedbeb5,0xbe443eb5,0x3eed3eb5,0x3e44beb5,0x3eed0000,0xbe44bf00,0xbeed0000,0x3e443f00,0xbe443eb5,0x3eed3eb5,0x3e44beb5,0xbeedbeb5,
0x3ee20000,0xbe71bf00,0xbe153eb5,0x3ef53eb5,0xbd493ed5,0x3eff3e8e,0xbea2befb,0xbec63dc8,0xbec6beed,0xbea23e44,0x3eff3e44,0xbd49beed,0x3ef53dc8,0xbe15befb,0xbe713e8e,0x3ee23ed5,
0xbe8ebf00,0xbed50000,0x3ed50000,0xbe8ebf00,0x3efb3e44,0xbdc8beed,0x3dc83eed,0x3efb3e44,0xbdc83eb5,0x3efb3eb5,0xbefbbeb5,0xbdc83eb5,0xbed5beed,0xbe8e3e44,0x3e8ebe44,0xbed5beed,
0xbec60000,0x3ea23f00,0xbeffbeb5,0xbd493eb5,0xbe71befb,0xbee2bdc8,0x3e15be8e,0xbef5bed5,0x3ef53e44,0xbe15beed,0x3ee23eed,0x3e71be44,0x3d493ed5,0x3eff3e8e,0xbea23dc8,0x3ec63efb,
0x3f003f00,0xbf003f00,0x3f003f00,0xbf003f00,0x3f003f00,0xbf003f00,0x3f003f00,0xbf003f00,0x3f003f00,0xbf003f00,0x3f003f00,0xbf003f00,0x3f003f00,0xbf003f00,0x3f003f00,0xbf003f00,
0xbeffbf00,0x3d490000,0xbea2beb5,0x3ec63eb5,0xbef5befb,0x3e153dc8,0xbe71be8e,0x3ee23ed5,0xbee2beed,0x3e713e44,0xbe15be44,0x3ef53eed,0xbec6bed5,0x3ea23e8e,0xbd49bdc8,0x3eff3efb,
0x3efb3f00,0xbdc80000,0xbdc80000,0xbefbbf00,0x3ed53eed,0xbe8ebe44,0xbe8ebe44,0xbed5beed,0x3e8e3eb5,0xbed5beb5,0xbed5beb5,0xbe8ebeb5,0x3dc83e44,0xbefbbeed,0xbefbbeed,0xbdc8be44,
0xbef5bf00,0x3e150000,0x3ee23eb5,0x3e713eb5,0xbea2bed5,0x3ec63e8e,0x3eff3efb,0xbd493dc8,0xbd49be44,0x3eff3eed,0x3ec63eed,0xbea2be44,0x3e713dc8,0x3ee23efb,0x3e153e8e,0xbef5bed5,
0x3eed3f00,0xbe440000,0xbeedbf00,0x3e440000,0x3e443eb5,0xbeedbeb5,0xbe44beb5,0x3eed3eb5,0xbe440000,0xbeedbf00,0x3e440000,0x3eed3f00,0xbeedbeb5,0xbe44beb5,0x3eed3eb5,0x3e443eb5,
0xbee2bf00,0x3e710000,0x3e153eb5,0xbef5beb5,0xbd49be8e,0x3eff3ed5,0xbea2bdc8,0xbec6befb,0x3ec63e44,0x3ea23eed,0xbeffbeed,0x3d49be44,0x3ef53efb,0xbe153dc8,0xbe71bed5,0x3ee23e8e,
0x3ed53f00,0xbe8e0000,0x3e8e0000,0x3ed53f00,0xbdc83e44,0xbefbbeed,0x3efb3eed,0xbdc83e44,0xbefbbeb5,0xbdc8beb5,0x3dc83eb5,0xbefbbeb5,0xbe8ebeed,0x3ed53e44,0xbed5be44,0xbe8ebeed,
0xbec6bf00,0x3ea20000,0xbeffbeb5,0xbd49beb5,0x3e71bdc8,0x3ee23efb,0xbe15bed5,0x3ef53e8e,0x3ef53eed,0xbe153e44,0x3ee23e44,0x3e713eed,0xbd493e8e,0xbeffbed5,0x3ea23efb,0xbec6bdc8,
0x3f00,0xbf000000,0x3f00,0xbf000000,0xbf00,0x3f000000,0xbf00,0x3f000000,0x3f00,0xbf000000,0x3f00,0xbf000000,0xbf00,0x3f000000,0xbf00,0x3f000000,
0x3d49bf00,0x3eff0000,0x3ec6beb5,0x3ea23eb5,0xbe153efb,0xbef5bdc8,0xbee23e8e,0xbe71bed5,0x3e71beed,0x3ee23e44,0x3ef5be44,0x3e153eed,0xbea23ed5,0xbec6be8e,0xbeff3dc8,0xbd49befb,
0xbdc83f00,0xbefb0000,0xbefb0000,0x3dc8bf00,0x3e8ebeed,0x3ed53e44,0x3ed53e44,0xbe8e3eed,0xbed53eb5,0xbe8ebeb5,0xbe8ebeb5,0x3ed5beb5,0x3efbbe44,0x3dc83eed,0x3dc83eed,0xbefb3e44,
0x3e15bf00,0x3ef50000,0x3e713eb5,0xbee23eb5,0xbec63ed5,0xbea2be8e,0x3d49befb,0x3effbdc8,0x3effbe44,0x3d493eed,0xbea23eed,0xbec6be44,0xbee2bdc8,0x3e71befb,0x3ef5be8e,0x3e153ed5,
0xbe443f00,0xbeed0000,0x3e44bf00,0x3eed0000,0x3eedbeb5,0x3e443eb5,0xbeed3eb5,0xbe44beb5,0xbeed0000,0x3e44bf00,0x3eed0000,0xbe443f00,0x3e443eb5,0xbeed3eb5,0xbe44beb5,0x3eedbeb5,
0x3e71bf00,0x3ee20000,0xbef53eb5,0xbe15beb5,0xbeff3e8e,0xbd49bed5,0x3ec63dc8,0xbea23efb,0x3ea23e44,0xbec63eed,0x3d49beed,0x3effbe44,0x3e15befb,0x3ef5bdc8,0xbee23ed5,0xbe71be8e,
0xbe8e3f00,0xbed50000,0x3ed50000,0xbe8e3f00,0x3efbbe44,0xbdc83eed,0x3dc8beed,0x3efbbe44,0xbdc8beb5,0x3efbbeb5,0xbefb3eb5,0xbdc8beb5,0xbed53eed,0xbe8ebe44,0x3e8e3e44,0xbed53eed,
0x3ea2bf00,0x3ec60000,0xbd49beb5,0x3effbeb5,0xbee23dc8,0x3e71befb,0xbef53ed5,0xbe15be8e,0xbe153eed,0xbef53e44,0x3e713e44,0xbee23eed,0x3effbe8e,0xbd493ed5,0x3ec6befb,0x3ea23dc8,
0x3eb53f00,0xbeb50000,0x3eb53f00,0xbeb50000,0xbeb50000,0xbeb5bf00,0xbeb50000,0xbeb5bf00,0xbeb5bf00,0x3eb50000,0xbeb5bf00,0x3eb50000,0x3eb50000,0x3eb53f00,0x3eb50000,0x3eb53f00,
0x3effbf00,0xbd490000,0x3ea2beb5,0xbec63eb5,0x3ef5befb,0xbe153dc8,0x3e71be8e,0xbee23ed5,0x3ee2beed,0xbe713e44,0x3e15be44,0xbef53eed,0x3ec6bed5,0xbea23e8e,0x3d49bdc8,0xbeff3efb,
0xbefb3f00,0x3dc80000,0x3dc80000,0x3efbbf00,0xbed53eed,0x3e8ebe44,0x3e8ebe44,0x3ed5beed,0xbe8e3eb5,0x3ed5beb5,0x3ed5beb5,0x3e8ebeb5,0xbdc83e44,0x3efbbeed,0x3efbbeed,0x3dc8be44,
0x3ef5bf00,0xbe150000,0xbee23eb5,0xbe713eb5,0x3ea2bed5,0xbec63e8e,0xbeff3efb,0x3d493dc8,0x3d49be44,0xbeff3eed,0xbec63eed,0x3ea2be44,0xbe713dc8,0xbee23efb,0xbe153e8e,0x3ef5bed5,
0xbeed3f00,0x3e440000,0x3eedbf00,0xbe440000,0xbe443eb5,0x3eedbeb5,0x3e44beb5,0xbeed3eb5,0x3e440000,0x3eedbf00,0xbe440000,0xbeed3f00,0x3eedbeb5,0x3e44beb5,0xbeed3eb5,0xbe443eb5,
0x3ee2bf00,0xbe710000,0xbe153eb5,0x3ef5beb5,0x3d49be8e,0xbeff3ed5,0x3ea2bdc8,0x3ec6befb,0xbec63e44,0xbea23eed,0x3effbeed,0xbd49be44,0xbef53efb,0x3e153dc8,0x3e71bed5,0xbee23e8e,
0xbed53f00,0x3e8e0000,0xbe8e0000,0xbed53f00,0x3dc83e44,0x3efbbeed,0xbefb3eed,0x3dc83e44,0x3efbbeb5,0x3dc8beb5,0xbdc83eb5,0x3efbbeb5,0x3e8ebeed,0xbed53e44,0x3ed5be44,0x3e8ebeed,
0x3ec6bf00,0xbea20000,0x3effbeb5,0x3d49beb5,0xbe71bdc8,0xbee23efb,0x3e15bed5,0xbef53e8e,0xbef53eed,0x3e153e44,0xbee23e44,0xbe713eed,0x3d493e8e,0x3effbed5,0xbea23efb,0x3ec6bdc8,
0xbeb53f00,0xbeb50000,0xbeb53f00,0xbeb50000,0x3eb50000,0xbeb53f00,0x3eb50000,0xbeb53f00,0x3eb5bf00,0x3eb50000,0x3eb5bf00,0x3eb50000,0xbeb50000,0x3eb5bf00,0xbeb50000,0x3eb5bf00,
0xbd49bf00,0xbeff0000,0xbec6beb5,0xbea23eb5,0x3e153efb,0x3ef5bdc8,0x3ee23e8e,0x3e71bed5,0xbe71beed,0xbee23e44,0xbef5be44,0xbe153eed,0x3ea23ed5,0x3ec6be8e,0x3eff3dc8,0x3d49befb,
0x3dc83f00,0x3efb0000,0x3efb0000,0xbdc8bf00,0xbe8ebeed,0xbed53e44,0xbed53e44,0x3e8e3eed,0x3ed53eb5,0x3e8ebeb5,0x3e8ebeb5,0xbed5beb5,0xbefbbe44,0xbdc83eed,0xbdc83eed,0x3efb3e44,
0xbe15bf00,0xbef50000,0xbe713eb5,0x3ee23eb5,0x3ec63ed5,0x3ea2be8e,0xbd49befb,0xbeffbdc8,0xbeffbe44,0xbd493eed,0x3ea23eed,0x3ec6be44,0x3ee2bdc8,0xbe71befb,0xbef5be8e,0xbe153ed5,
0x3e443f00,0x3eed0000,0xbe44bf00,0xbeed0000,0xbeedbeb5,0xbe443eb5,0x3eed3eb5,0x3e44beb5,0x3eed0000,0xbe44bf00,0xbeed0000,0x3e443f00,0xbe443eb5,0x3eed3eb5,0x3e44beb5,0xbeedbeb5,
0xbe71bf00,0xbee20000,0x3ef53eb5,0x3e15beb5,0x3eff3e8e,0x3d49bed5,0xbec63dc8,0x3ea23efb,0xbea23e44,0x3ec63eed,0xbd49beed,0xbeffbe44,0xbe15befb,0xbef5bdc8,0x3ee23ed5,0x3e71be8e,
0x3e8e3f00,0x3ed50000,0xbed50000,0x3e8e3f00,0xbefbbe44,0x3dc83eed,0xbdc8beed,0xbefbbe44,0x3dc8beb5,0xbefbbeb5,0x3efb3eb5,0x3dc8beb5,0x3ed53eed,0x3e8ebe44,0xbe8e3e44,0x3ed53eed,
0xbea2bf00,0xbec60000,0x3d49beb5,0xbeffbeb5,0x3ee23dc8,0xbe71befb,0x3ef53ed5,0x3e15be8e,0x3e153eed,0x3ef53e44,0xbe713e44,0x3ee23eed,0xbeffbe8e,0x3d493ed5,0xbec6befb,0xbea23dc8,
0x3f003f00,0xbf003f00,0x3f003f00,0xbf003f00,0x3f003f00,0xbf003f00,0x3f003f00,0xbf003f00,0x3f003f00,0xbf003f00,0x3f003f00,0xbf003f00,0x3f003f00,0xbf003f00,0x3f003f00,0xbf003f00,
0x3d490000,0x3eff3f00,0x3ec63eb5,0x3ea23eb5,0x3e153dc8,0x3ef53efb,0x3ee23ed5,0x3e713e8e,0x3e713e44,0x3ee23eed,0x3ef53eed,0x3e153e44,0x3ea23e8e,0x3ec63ed5,0x3eff3efb,0x3d493dc8,
0xbefbbf00,0x3dc80000,0x3dc80000,0x3efb3f00,0xbed5beed,0x3e8e3e44,0x3e8e3e44,0x3ed53eed,0xbe8ebeb5,0x3ed53eb5,0x3ed53eb5,0x3e8e3eb5,0xbdc8be44,0x3efb3eed,0x3efb3eed,0x3dc83e44,
0xbe150000,0xbef5bf00,0xbe71beb5,0x3ee23eb5,0xbec6be8e,0xbea2bed5,0x3d49bdc8,0x3eff3efb,0xbeffbeed,0xbd49be44,0x3ea23e44,0x3ec63eed,0xbee2befb,0x3e713dc8,0x3ef53ed5,0x3e153e8e,
0x3eed3f00,0xbe440000,0xbeedbf00,0x3e440000,0x3e443eb5,0xbeedbeb5,0xbe44beb5,0x3eed3eb5,0xbe440000,0xbeedbf00,0x3e440000,0x3eed3f00,0xbeedbeb5,0xbe44beb5,0x3eed3eb5,0x3e443eb5,
0x3e710000,0x3ee23f00,0xbef5beb5,0xbe15beb5,0x3eff3ed5,0x3d493e8e,0xbec6befb,0x3ea23dc8,0x3ea23eed,0xbec6be44,0x3d49be44,0x3eff3eed,0xbe153dc8,0xbef5befb,0x3ee23e8e,0x3e713ed5,
0xbed5bf00,0x3e8e0000,0xbe8e0000,0xbed5bf00,0x3dc8be44,0x3efb3eed,0xbefbbeed,0x3dc8be44,0x3efb3eb5,0x3dc83eb5,0xbdc8beb5,0x3efb3eb5,0x3e8e3eed,0xbed5be44,0x3ed53e44,0x3e8e3eed,
0xbea20000,0xbec6bf00,0x3d493eb5,0xbeffbeb5,0xbee2befb,0x3e71bdc8,0xbef5be8e,0xbe15bed5,0x3e15be44,0x3ef53eed,0xbe71beed,0x3ee23e44,0x3eff3ed5,0xbd493e8e,0x3ec63dc8,0x3ea23efb,
0x3f00,0xbf000000,0x3f00,0xbf000000,0xbf00,0x3f000000,0xbf00,0x3f000000,0x3f00,0xbf000000,0x3f00,0xbf000000,0xbf00,0x3f000000,0xbf00,0x3f000000,
0x3eff0000,0xbd493f00,0x3ea23eb5,0xbec63eb5,0xbef5bdc8,0x3e15befb,0xbe71bed5,0x3ee2be8e,0x3ee23e44,0xbe713eed,0x3e153eed,0xbef53e44,0xbec6be8e,0x3ea2bed5,0xbd49befb,0x3effbdc8,
0x3dc8bf00,0x3efb0000,0x3efb0000,0xbdc83f00,0xbe8e3eed,0xbed5be44,0xbed5be44,0x3e8ebeed,0x3ed5beb5,0x3e8e3eb5,0x3e8e3eb5,0xbed53eb5,0xbefb3e44,0xbdc8beed,0xbdc8beed,0x3efbbe44,
0xbef50000,0x3e15bf00,0x3ee2beb5,0x3e713eb5,0x3ea23e8e,0xbec63ed5,0xbeff3dc8,0x3d49befb,0xbd49beed,0x3effbe44,0x3ec63e44,0xbea23eed,0xbe713efb,0xbee2bdc8,0xbe15bed5,0x3ef5be8e,
0xbe443f00,0xbeed0000,0x3e44bf00,0x3eed0000,0x3eedbeb5,0x3e443eb5,0xbeed3eb5,0xbe44beb5,0xbeed0000,0x3e44bf00,0x3eed0000,0xbe443f00,0x3e443eb5,0xbeed3eb5,0xbe44beb5,0x3eedbeb5,
0x3ee20000,0xbe713f00,0xbe15beb5,0x3ef5beb5,0xbd49bed5,0x3effbe8e,0xbea23efb,0xbec6bdc8,0xbec63eed,0xbea2be44,0x3effbe44,0xbd493eed,0x3ef5bdc8,0xbe153efb,0xbe71be8e,0x3ee2bed5,
0x3e8ebf00,0x3ed50000,0xbed50000,0x3e8ebf00,0xbefb3e44,0x3dc8beed,0xbdc83eed,0xbefb3e44,0x3dc83eb5,0xbefb3eb5,0x3efbbeb5,0x3dc83eb5,0x3ed5beed,0x3e8e3e44,0xbe8ebe44,0x3ed5beed,
0xbec60000,0x3ea2bf00,0xbeff3eb5,0xbd49beb5,0xbe713efb,0xbee23dc8,0x3e153e8e,0xbef53ed5,0x3ef5be44,0xbe153eed,0x3ee2beed,0x3e713e44,0x3d49bed5,0x3effbe8e,0xbea2bdc8,0x3ec6befb,
0x3eb53f00,0xbeb50000,0x3eb53f00,0xbeb50000,0xbeb50000,0xbeb5bf00,0xbeb50000,0xbeb5bf00,0xbeb5bf00,0x3eb50000,0xbeb5bf00,0x3eb50000,0x3eb50000,0x3eb53f00,0x3eb50000,0x3eb53f00,
0xbd490000,0xbeff3f00,0xbec63eb5,0xbea23eb5,0xbe153dc8,0xbef53efb,0xbee23ed5,0xbe713e8e,0xbe713e44,0xbee23eed,0xbef53eed,0xbe153e44,0xbea23e8e,0xbec63ed5,0xbeff3efb,0xbd493dc8,
0x3efbbf00,0xbdc80000,0xbdc80000,0xbefb3f00,0x3ed5beed,0xbe8e3e44,0xbe8e3e44,0xbed53eed,0x3e8ebeb5,0xbed53eb5,0xbed53eb5,0xbe8e3eb5,0x3dc8be44,0xbefb3eed,0xbefb3eed,0xbdc83e44,
0x3e150000,0x3ef5bf00,0x3e71beb5,0xbee23eb5,0x3ec6be8e,0x3ea2bed5,0xbd49bdc8,0xbeff3efb,0x3effbeed,0x3d49be44,0xbea23e44,0xbec63eed,0x3ee2befb,0xbe713dc8,0xbef53ed5,0xbe153e8e,
0xbeed3f00,0x3e440000,0x3eedbf00,0xbe440000,0xbe443eb5,0x3eedbeb5,0x3e44beb5,0xbeed3eb5,0x3e440000,0x3eedbf00,0xbe440000,0xbeed3f00,0x3eedbeb5,0x3e44beb5,0xbeed3eb5,0xbe443eb5,
0xbe710000,0xbee23f00,0x3ef5beb5,0x3e15beb5,0xbeff3ed5,0xbd493e8e,0x3ec6befb,0xbea23dc8,0xbea23eed,0x3ec6be44,0xbd49be44,0xbeff3eed,0x3e153dc8,0x3ef5befb,0xbee23e8e,0xbe713ed5,
0x3ed5bf00,0xbe8e0000,0x3e8e0000,0x3ed5bf00,0xbdc8be44,0xbefb3eed,0x3efbbeed,0xbdc8be44,0xbefb3eb5,0xbdc83eb5,0x3dc8beb5,0xbefb3eb5,0xbe8e3eed,0x3ed5be44,0xbed53e44,0xbe8e3eed,
0x3ea20000,0x3ec6bf00,0xbd493eb5,0x3effbeb5,0x3ee2befb,0xbe71bdc8,0x3ef5be8e,0x3e15bed5,0xbe15be44,0xbef53eed,0x3e71beed,0xbee23e44,0xbeff3ed5,0x3d493e8e,0xbec63dc8,0xbea23efb,
0xbeb53f00,0xbeb50000,0xbeb53f00,0xbeb50000,0x3eb50000,0xbeb53f00,0x3eb50000,0xbeb53f00,0x3eb5bf00,0x3eb50000,0x3eb5bf00,0x3eb50000,0xbeb50000,0x3eb5bf00,0xbeb50000,0x3eb5bf00,
0xbeff0000,0x3d493f00,0xbea23eb5,0x3ec63eb5,0x3ef5bdc8,0xbe15befb,0x3e71bed5,0xbee2be8e,0xbee23e44,0x3e713eed,0xbe153eed,0x3ef53e44,0x3ec6be8e,0xbea2bed5,0x3d49befb,0xbeffbdc8,
0xbdc8bf00,0xbefb0000,0xbefb0000,0x3dc83f00,0x3e8e3eed,0x3ed5be44,0x3ed5be44,0xbe8ebeed,0xbed5beb5,0xbe8e3eb5,0xbe8e3eb5,0x3ed53eb5,0x3efb3e44,0x3dc8beed,0x3dc8beed,0xbefbbe44,
0x3ef50000,0xbe15bf00,0xbee2beb5,0xbe713eb5,0xbea23e8e,0x3ec63ed5,0x3eff3dc8,0xbd49befb,0x3d49beed,0xbeffbe44,0xbec63e44,0x3ea23eed,0x3e713efb,0x3ee2bdc8,0x3e15bed5,0xbef5be8e,
0x3e443f00,0x3eed0000,0xbe44bf00,0xbeed0000,0xbeedbeb5,0xbe443eb5,0x3eed3eb5,0x3e44beb5,0x3eed0000,0xbe44bf00,0xbeed0000,0x3e443f00,0xbe443eb5,0x3eed3eb5,0x3e44beb5,0xbeedbeb5,
0xbee20000,0x3e713f00,0x3e15beb5,0xbef5beb5,0x3d49bed5,0xbeffbe8e,0x3ea23efb,0x3ec6bdc8,0x3ec63eed,0x3ea2be44,0xbeffbe44,0x3d493eed,0xbef5bdc8,0x3e153efb,0x3e71be8e,0xbee2bed5,
0xbe8ebf00,0xbed50000,0x3ed50000,0xbe8ebf00,0x3efb3e44,0xbdc8beed,0x3dc83eed,0x3efb3e44,0xbdc83eb5,0x3efb3eb5,0xbefbbeb5,0xbdc83eb5,0xbed5beed,0xbe8e3e44,0x3e8ebe44,0xbed5beed,
0x3ec60000,0xbea2bf00,0x3eff3eb5,0x3d49beb5,0x3e713efb,0x3ee23dc8,0xbe153e8e,0x3ef53ed5,0xbef5be44,0x3e153eed,0xbee2beed,0xbe713e44,0xbd49bed5,0xbeffbe8e,0x3ea2bdc8,0xbec6befb,
0x3f800000,0x0,0x3f800000,0x0,0x3f800000,0x0,0x3f800000,0x0,0x3f800000,0x0,0x3f800000,0x0,0x3f800000,0x0,0x3f800000,0x0,
0x3f800000,0x0,0x3f7fec43,0xbcc90ab0,0x3f7fb10f,0xbd48fb30,0x3f7f4e6d,0xbd96a905,0x3f7ec46d,0xbdc8bd36,0x3f7e1324,0xbdfab273,0x3f7d3aac,0xbe164083,0x3f7c3b28,0xbe2f10a2,
0x3f800000,0x0,0x3f7ffec4,0xbbc90f88,0x3f7ffb11,0xbc490e90,0x3f7ff4e6,0xbc96c9b6,0x3f7fec43,0xbcc90ab0,0x3f7fe129,0xbcfb49ba,0x3f7fd397,0xbd16c32c,0x3f7fc38f,0xbd2fe007,
0x3f800000,0x0,0x3f7fe129,0xbcfb49ba,0x3f7f84ab,0xbd7b2b74,0x3f7eea9d,0xbdbc3ac3,0x3f7e1324,0xbdfab273,0x3f7cfe73,0xbe1c76de,0x3f7baccd,0xbe3b6ecf,0x3f7a1e84,0xbe5a3997,
0x3f800000,0x0,0x3f7ffb11,0xbc490e90,0x3f7fec43,0xbcc90ab0,0x3f7fd397,0xbd16c32c,0x3f7fb10f,0xbd48fb30,0x3f7f84ab,0xbd7b2b74,0x3f7f4e6d,0xbd96a905,0x3f7f0e58,0xbdafb680,
0x3f800000,0x0,0x3f7fd397,0xbd16c32c,0x3f7f4e6d,0xbd96a905,0x3f7e70b0,0xbde1bc2e,0x3f7d3aac,0xbe164083,0x3f7baccd,0xbe3b6ecf,0x3f79c79d,0xbe605c13,0x3f778bc5,0xbe827dc0,
0x3f800000,0x0,0x3f7ff4e6,0xbc96c9b6,0x3f7fd397,0xbd16c32c,0x3f7f9c18,0xbd621469,0x3f7f4e6d,0xbd96a905,0x3f7eea9d,0xbdbc3ac3,0x3f7e70b0,0xbde1bc2e,0x3f7de0b1,0xbe039502,
0x3f800000,0x0,0x3f7fc38f,0xbd2fe007,0x3f7f0e58,0xbdafb680,0x3f7de0b1,0xbe039502,0x3f7c3b28,0xbe2f10a2,0x3f7a1e84,0xbe5a3997,0x3f778bc5,0xbe827dc0,0x3f748422,0xbe97a117,
0x3f800000,0x0,0x3f7fb10f,0xbd48fb30,0x3f7ec46d,0xbdc8bd36,0x3f7d3aac,0xbe164083,0x3f7b14be,0xbe47c5c2,0x3f7853f8,0xbe78cfcc,0x3f74fa0b,0xbe94a031,0x3f710908,0xbeac7cd4,
0x3f800000,0x0,0x3f7f4e6d,0xbd96a905,0x3f7d3aac,0xbe164083,0x3f79c79d,0xbe605c13,0x3f74fa0b,0xbe94a031,0x3f6ed89e,0xbeb8442a,0x3f676bd8,0xbedae880,0x3f5ebe05,0xbefc5d27,
0x3f800000,0x0,0x3f7f9c18,0xbd621469,0x3f7e70b0,0xbde1bc2e,0x3f7c7eb0,0xbe28defc,0x3f79c79d,0xbe605c13,0x3f764d97,0xbe8b9507,0x3f721352,0xbea68f12,0x3f6d1c1d,0xbec1071e,
0x3f800000,0x0,0x3f7f2f9d,0xbda3308c,0x3f7cbfc9,0xbe22abb6,0x3f78b47b,0xbe72b651,0x3f731447,0xbea09ae5,0x3f6be858,0xbec6d529,0x3f633c5a,0xbeebcbbb,0x3f591e6a,0xbf07a136,
0x3f800000,0x0,0x3f7f84ab,0xbd7b2b74,0x3f7e1324,0xbdfab273,0x3f7baccd,0xbe3b6ecf,0x3f7853f8,0xbe78cfcc,0x3f740bdd,0xbe9aa086,0x3f6ed89e,0xbeb8442a,0x3f68bf3c,0xbed53641,
0x3f800000,0x0,0x3f7f0e58,0xbdafb680,0x3f7c3b28,0xbe2f10a2,0x3f778bc5,0xbe827dc0,0x3f710908,0xbeac7cd4,0x3f68bf3c,0xbed53641,0x3f5ebe05,0xbefc5d27,0x3f531849,0xbf10d3cd,
0x3f800000,0x0,0x3f7f6ac7,0xbd8a200a,0x3f7dabcc,0xbe09cf86,0x3f7ac516,0xbe4dee60,0x3f76ba07,0xbe888e93,0x3f718f57,0xbea986c4,0x3f6b4b0c,0xbec9b953,0x3f63f473,0xbee900b7,
0x3f800000,0x0,0x3f7eea9d,0xbdbc3ac3,0x3f7baccd,0xbe3b6ecf,0x3f764d97,0xbe8b9507,0x3f6ed89e,0xbeb8442a,0x3f655e0b,0xbee363fa,0x3f59f26a,0xbf064b82,0x3f4cae79,0xbf19c200,
0x3f800000,0x0,0x3f7ec46d,0xbdc8bd36,0x3f7b14be,0xbe47c5c2,0x3f74fa0b,0xbe94a031,0x3f6c835e,0xbec3ef15,0x3f61c598,0xbef15aea,0x3f54db31,0xbf0e39da,0x3f45e403,0xbf226799,
0x3f800000,0x0,0x3f7e1324,0xbdfab273,0x3f7853f8,0xbe78cfcc,0x3f6ed89e,0xbeb8442a,0x3f61c598,0xbef15aea,0x3f514d3d,0xbf13682a,0x3f3daef9,0xbf2beb4a,0x3f273656,0xbf41d870,
0x3f800000,0x0,0x3f7e9bc9,0xbdd53db9,0x3f7a7302,0xbe541501,0x3f73913f,0xbe9d9e78,0x3f6a09a7,0xbecf7bca,0x3f5df6be,0xbeff17b2,0x3f4f7a1f,0xbf15f6d9,0x3f3ebc1b,0xbf2ac082,
0x3f800000,0x0,0x3f7de0b1,0xbe039502,0x3f778bc5,0xbe827dc0,0x3f6d1c1d,0xbec1071e,0x3f5ebe05,0xbefc5d27,0x3f4cae79,0xbf19c200,0x3f373a23,0xbf32c8c9,0x3f1ebc12,0xbf48d8b3,
0x3f800000,0x0,0x3f7e70b0,0xbde1bc2e,0x3f79c79d,0xbe605c13,0x3f721352,0xbea68f12,0x3f676bd8,0xbedae880,0x3f59f26a,0xbf064b82,0x3f49d112,0xbf1d7fd1,0x3f373a23,0xbf32c8c9,
0x3f800000,0x0,0x3f7dabcc,0xbe09cf86,0x3f76ba07,0xbe888e93,0x3f6b4b0c,0xbec9b953,0x3f5b941a,0xbf039c3d,0x3f47de65,0xbf1ff6cb,0x3f3085bb,0xbf396842,0x3f15f6d9,0xbf4f7a1f,
0x3f800000,0x0,0x3f7e4323,0xbdee3876,0x3f791298,0xbe6c9a7f,0x3f708066,0xbeaf713a,0x3f64aa59,0xbee63375,0x3f55b993,0xbf0cead0,0x3f43e200,0xbf24d225,0x3f2f61a5,0xbf3a7ca4,
0x3f800000,0x0,0x3f7d7474,0xbe1008b7,0x3f75dec6,0xbe8e9a22,0x3f696591,0xbed25a09,0x3f584853,0xbf08f59b,0x3f42de29,0xbf26050a,0x3f299415,0xbf3fc767,0x3f0cead0,0xbf55b993,
0x3f800000,0x0,0x3f7d3aac,0xbe164083,0x3f74fa0b,0xbe94a031,0x3f676bd8,0xbedae880,0x3f54db31,0xbf0e39da,0x3f3daef9,0xbf2beb4a,0x3f226799,0xbf45e403,0x3f039c3d,0xbf5b941a,
0x3f800000,0x0,0x3f7c3b28,0xbe2f10a2,0x3f710908,0xbeac7cd4,0x3f5ebe05,0xbefc5d27,0x3f45e403,0xbf226799,0x3f273656,0xbf41d870,0x3f039c3d,0xbf5b941a,0x3eb8442a,0xbf6ed89e,
0x3f800000,0x0,0x3f7cfe73,0xbe1c76de,0x3f740bdd,0xbe9aa086,0x3f655e0b,0xbee363fa,0x3f514d3d,0xbf13682a,0x3f385216,0xbf31a81d,0x3f1b02c6,0xbf4bbbf8,0x3ef41f07,0xbf6106f2,
0x3f800000,0x0,0x3f7bf531,0xbe354098,0x3f6ff573,0xbeb263ef,0x3f5c61c7,0xbf0242b1,0x3f41d870,0xbf273656,0x3f212ff9,0xbf46e22a,0x3ef6e0cb,0xbf604621,0x3ea395c5,0xbf7294f8,
0x3f800000,0x0,0x3f7cbfc9,0xbe22abb6,0x3f731447,0xbea09ae5,0x3f633c5a,0xbeebcbbb,0x3f4d9f02,0xbf187fc0,0x3f32c8c9,0xbf373a23,0x3f13682a,0xbf514d3d,0x3ee0924f,0xbf660f88,
0x3f800000,0x0,0x3f7baccd,0xbe3b6ecf,0x3f6ed89e,0xbeb8442a,0x3f59f26a,0xbf064b82,0x3f3daef9,0xbf2beb4a,0x3f1b02c6,0xbf4bbbf8,0x3ee63375,0xbf64aa59,0x3e8e9a22,0xbf75dec6,
0x3f800000,0x0,0x3f7c7eb0,0xbe28defc,0x3f721352,0xbea68f12,0x3f6106f2,0xbef41f07,0x3f49d112,0xbf1d7fd1,0x3f2d1469,0xbf3ca003,0x3f0b9a6b,0xbf5695e5,0x3ecc9b8b,0xbf6aab7b,
0x3f800000,0x0,0x3f7b61fc,0xbe419b37,0x3f6db293,0xbebe1d4a,0x3f577026,0xbf0a48ad,0x3f396842,0xbf3085bb,0x3f14b039,0xbf5064af,0x3ed53641,0xbf68bf3c,0x3e72b651,0xbf78b47b,
0x3f800000,0x0,0x3f800000,0x0,0x3f800000,0x0,0x3f800000,0x0,0x3f800000,0x0,0x3f800000,0x0,0x3f800000,0x0,0x3f800000,0x0,
0x3f7b14be,0xbe47c5c2,0x3f79c79d,0xbe605c13,0x3f7853f8,0xbe78cfcc,0x3f76ba07,0xbe888e93,0x3f74fa0b,0xbe94a031,0x3f731447,0xbea09ae5,0x3f710908,0xbeac7cd4,0x3f6ed89e,0xbeb8442a,
0x3f7fb10f,0xbd48fb30,0x3f7f9c18,0xbd621469,0x3f7f84ab,0xbd7b2b74,0x3f7f6ac7,0xbd8a200a,0x3f7f4e6d,0xbd96a905,0x3f7f2f9d,0xbda3308c,0x3f7f0e58,0xbdafb680,0x3f7eea9d,0xbdbc3ac3,
0x3f7853f8,0xbe78cfcc,0x3f764d97,0xbe8b9507,0x3f740bdd,0xbe9aa086,0x3f718f57,0xbea986c4,0x3f6ed89e,0xbeb8442a,0x3f6be858,0xbec6d529,0x3f68bf3c,0xbed53641,0x3f655e0b,0xbee363fa,
0x3f7ec46d,0xbdc8bd36,0x3f7e70b0,0xbde1bc2e,0x3f7e1324,0xbdfab273,0x3f7dabcc,0xbe09cf86,0x3f7d3aac,0xbe164083,0x3f7cbfc9,0xbe22abb6,0x3f7c3b28,0xbe2f10a2,0x3f7baccd,0xbe3b6ecf,
0x3f74fa0b,0xbe94a031,0x3f721352,0xbea68f12,0x3f6ed89e,0xbeb8442a,0x3f6b4b0c,0xbec9b953,0x3f676bd8,0xbedae880,0x3f633c5a,0xbeebcbbb,0x3f5ebe05,0xbefc5d27,0x3f59f26a,0xbf064b82,
0x3f7d3aac,0xbe164083,0x3f7c7eb0,0xbe28defc,0x3f7baccd,0xbe3b6ecf,0x3f7ac516,0xbe4dee60,0x3f79c79d,0xbe605c13,0x3f78b47b,0xbe72b651,0x3f778bc5,0xbe827dc0,0x3f764d97,0xbe8b9507,
0x3f710908,0xbeac7cd4,0x3f6d1c1d,0xbec1071e,0x3f68bf3c,0xbed53641,0x3f63f473,0xbee900b7,0x3f5ebe05,0xbefc5d27,0x3f591e6a,0xbf07a136,0x3f531849,0xbf10d3cd,0x3f4cae79,0xbf19c200,
0x3f6c835e,0xbec3ef15,0x3f676bd8,0xbedae880,0x3f61c598,0xbef15aea,0x3f5b941a,0xbf039c3d,0x3f54db31,0xbf0e39da,0x3f4d9f02,0xbf187fc0,0x3f45e403,0xbf226799,0x3f3daef9,0xbf2beb4a,
0x3f54db31,0xbf0e39da,0x3f49d112,0xbf1d7fd1,0x3f3daef9,0xbf2beb4a,0x3f3085bb,0xbf396842,0x3f226799,0xbf45e403,0x3f13682a,0xbf514d3d,0x3f039c3d,0xbf5b941a,0x3ee63375,0xbf64aa59,
0x3f676bd8,0xbedae880,0x3f6106f2,0xbef41f07,0x3f59f26a,0xbf064b82,0x3f5233c6,0xbf121eb0,0x3f49d112,0xbf1d7fd1,0x3f40d0da,0xbf286605,0x3f373a23,0xbf32c8c9,0x3f2d1469,0xbf3ca003,
0x3f4d9f02,0xbf187fc0,0x3f40d0da,0xbf286605,0x3f32c8c9,0xbf373a23,0x3f239da9,0xbf44e3f5,0x3f13682a,0xbf514d3d,0x3f0242b1,0xbf5c61c7,0x3ee0924f,0xbf660f88,0x3ebb31a0,0xbf6e46be,
0x3f61c598,0xbef15aea,0x3f59f26a,0xbf064b82,0x3f514d3d,0xbf13682a,0x3f47de65,0xbf1ff6cb,0x3f3daef9,0xbf2beb4a,0x3f32c8c9,0xbf373a23,0x3f273656,0xbf41d870,0x3f1b02c6,0xbf4bbbf8,
0x3f45e403,0xbf226799,0x3f373a23,0xbf32c8c9,0x3f273656,0xbf41d870,0x3f15f6d9,0xbf4f7a1f,0x3f039c3d,0xbf5b941a,0x3ee0924f,0xbf660f88,0x3eb8442a,0xbf6ed89e,0x3e8e9a22,0xbf75dec6,
0x3f5b941a,0xbf039c3d,0x3f5233c6,0xbf121eb0,0x3f47de65,0xbf1ff6cb,0x3f3ca003,0xbf2d1469,0x3f3085bb,0xbf396842,0x3f239da9,0xbf44e3f5,0x3f15f6d9,0xbf4f7a1f,0x3f07a136,0xbf591e6a,
0x3f3daef9,0xbf2beb4a,0x3f2d1469,0xbf3ca003,0x3f1b02c6,0xbf4bbbf8,0x3f07a136,0xbf591e6a,0x3ee63375,0xbf64aa59,0x3ebb31a0,0xbf6e46be,0x3e8e9a22,0xbf75dec6,0x3e419b37,0xbf7b61fc,
0x3f3504f3,0xbf3504f3,0x3f226799,0xbf45e403,0x3f0e39da,0xbf54db31,0x3ef15aea,0xbf61c598,0x3ec3ef15,0xbf6c835e,0x3e94a031,0xbf74fa0b,0x3e47c5c2,0xbf7b14be,0x3dc8bd36,0xbf7ec46d,
0x3f0e39da,0xbf54db31,0x3ee63375,0xbf64aa59,0x3eac7cd4,0xbf710908,0x3e605c13,0xbf79c79d,0x3dc8bd36,0xbf7ec46d,0xbcc90ab0,0xbf7fec43,0xbe164083,0xbf7d3aac,0xbe888e93,0xbf76ba07,
0x3f2beb4a,0xbf3daef9,0x3f173c07,0xbf4e8d90,0x3f00e7e4,0xbf5d2d53,0x3ed25a09,0xbf696591,0x3ea09ae5,0xbf731447,0x3e5a3997,0xbf7a1e84,0x3de1bc2e,0xbf7e70b0,0x3bc90f88,0xbf7ffec4,
0x3f039c3d,0xbf5b941a,0x3ecc9b8b,0xbf6aab7b,0x3e8e9a22,0xbf75dec6,0x3e1c76de,0xbf7cfe73,0x3cc90ab0,0xbf7fec43,0xbdd53db9,0xbf7e9bc9,0xbe6c9a7f,0xbf791298,0xbeb554ec,0xbf6f6830,
0x3f226799,0xbf45e403,0x3f0b9a6b,0xbf5695e5,0x3ee63375,0xbf64aa59,0x3eb263ef,0xbf6ff573,0x3e78cfcc,0xbf7853f8,0x3e09cf86,0xbf7dabcc,0x3cc90ab0,0xbf7fec43,0xbdafb680,0xbf7f0e58,
0x3ef15aea,0xbf61c598,0x3eb263ef,0xbf6ff573,0x3e605c13,0xbf79c79d,0x3dafb680,0xbf7f0e58,0xbd48fb30,0xbf7fb10f,0xbe3b6ecf,0xbf7baccd,0xbea09ae5,0xbf731447,0xbee0924f,0xbf660f88,
0x3f187fc0,0xbf4d9f02,0x3eff17b2,0xbf5df6be,0x3ec9b953,0xbf6b4b0c,0x3e919ddd,0xbf756d97,0x3e2f10a2,0xbf7c3b28,0x3d621469,0xbf7f9c18,0xbd7b2b74,0xbf7f84ab,0xbe354098,0xbf7bf531,
0x3edae880,0xbf676bd8,0x3e97a117,0xbf748422,0x3e22abb6,0xbf7cbfc9,0x3c96c9b6,0xbf7ff4e6,0xbdfab273,0xbf7e1324,0xbe8586ce,0xbf772417,0xbec9b953,0xbf6b4b0c,0xbf04f484,0xbf5ac450,
0x3ec3ef15,0xbf6c835e,0x3e78cfcc,0xbf7853f8,0x3dc8bd36,0xbf7ec46d,0xbd48fb30,0xbf7fb10f,0xbe47c5c2,0xbf7b14be,0xbeac7cd4,0xbf710908,0xbef15aea,0xbf61c598,0xbf187fc0,0xbf4d9f02,
0x3e47c5c2,0xbf7b14be,0x3cc90ab0,0xbf7fec43,0xbe164083,0xbf7d3aac,0xbea09ae5,0xbf731447,0xbef15aea,0xbf61c598,0xbf1d7fd1,0xbf49d112,0xbf3daef9,0xbf2beb4a,0xbf584853,0xbf08f59b,
0x3eac7cd4,0xbf710908,0x3e419b37,0xbf7b61fc,0x3d16c32c,0xbf7fd397,0xbdee3876,0xbf7e4323,0xbe888e93,0xbf76ba07,0xbed25a09,0xbf696591,0xbf0b9a6b,0xbf5695e5,0xbf2ac082,0xbf3ebc1b,
0x3e164083,0xbf7d3aac,0xbcfb49ba,0xbf7fe129,0xbe541501,0xbf7a7302,0xbec1071e,0xbf6d1c1d,0xbf08f59b,0xbf584853,0xbf2d1469,0xbf3ca003,0xbf4bbbf8,0xbf1b02c6,0xbf63f473,0xbee900b7,
0x3e94a031,0xbf74fa0b,0x3e09cf86,0xbf7dabcc,0xbcc90ab0,0xbf7fec43,0xbe3b6ecf,0xbf7baccd,0xbeac7cd4,0xbf710908,0xbef6e0cb,0xbf604621,0xbf1d7fd1,0xbf49d112,0xbf3b8f3b,0xbf2e3bde,
0x3dc8bd36,0xbf7ec46d,0xbdafb680,0xbf7f0e58,0xbe888e93,0xbf76ba07,0xbee0924f,0xbf660f88,0xbf187fc0,0xbf4d9f02,0xbf3b8f3b,0xbf2e3bde,0xbf584853,0xbf08f59b,0xbf6db293,0xbebe1d4a,
0x3e78cfcc,0xbf7853f8,0x3da3308c,0xbf7f2f9d,0xbdafb680,0xbf7f0e58,0xbe7ee6e1,0xbf77f110,0xbecf7bca,0xbf6a09a7,0xbf0cead0,0xbf55b993,0xbf2e3bde,0xbf3b8f3b,0xbf4ac77f,0xbf1c420c,
0x3d48fb30,0xbf7fb10f,0xbe1008b7,0xbf7d7474,0xbea68f12,0xbf721352,0xbeff17b2,0xbf5df6be,0xbf273656,0xbf41d870,0xbf48d8b3,0xbf1ebc12,0xbf633c5a,0xbeebcbbb,0xbf756d97,0xbe919ddd,
0x3f800000,0x0,0x3f800000,0x0,0x3f800000,0x0,0x3f800000,0x0,0x3f800000,0x0,0x3f800000,0x0,0x3f800000,0x0,0x3f800000,0x0,
0x3f6c835e,0xbec3ef15,0x3f6a09a7,0xbecf7bca,0x3f676bd8,0xbedae880,0x3f64aa59,0xbee63375,0x3f61c598,0xbef15aea,0x3f5ebe05,0xbefc5d27,0x3f5b941a,0xbf039c3d,0x3f584853,0xbf08f59b,
0x3f7ec46d,0xbdc8bd36,0x3f7e9bc9,0xbdd53db9,0x3f7e70b0,0xbde1bc2e,0x3f7e4323,0xbdee3876,0x3f7e1324,0xbdfab273,0x3f7de0b1,0xbe039502,0x3f7dabcc,0xbe09cf86,0x3f7d7474,0xbe1008b7,
0x3f61c598,0xbef15aea,0x3f5df6be,0xbeff17b2,0x3f59f26a,0xbf064b82,0x3f55b993,0xbf0cead0,0x3f514d3d,0xbf13682a,0x3f4cae79,0xbf19c200,0x3f47de65,0xbf1ff6cb,0x3f42de29,0xbf26050a,
0x3f7b14be,0xbe47c5c2,0x3f7a7302,0xbe541501,0x3f79c79d,0xbe605c13,0x3f791298,0xbe6c9a7f,0x3f7853f8,0xbe78cfcc,0x3f778bc5,0xbe827dc0,0x3f76ba07,0xbe888e93,0x3f75dec6,0xbe8e9a22,
0x3f54db31,0xbf0e39da,0x3f4f7a1f,0xbf15f6d9,0x3f49d112,0xbf1d7fd1,0x3f43e200,0xbf24d225,0x3f3daef9,0xbf2beb4a,0x3f373a23,0xbf32c8c9,0x3f3085bb,0xbf396842,0x3f299415,0xbf3fc767,
0x3f74fa0b,0xbe94a031,0x3f73913f,0xbe9d9e78,0x3f721352,0xbea68f12,0x3f708066,0xbeaf713a,0x3f6ed89e,0xbeb8442a,0x3f6d1c1d,0xbec1071e,0x3f6b4b0c,0xbec9b953,0x3f696591,0xbed25a09,
0x3f45e403,0xbf226799,0x3f3ebc1b,0xbf2ac082,0x3f373a23,0xbf32c8c9,0x3f2f61a5,0xbf3a7ca4,0x3f273656,0xbf41d870,0x3f1ebc12,0xbf48d8b3,0x3f15f6d9,0xbf4f7a1f,0x3f0cead0,0xbf55b993,
0x3f3504f3,0xbf3504f3,0x3f2beb4a,0xbf3daef9,0x3f226799,0xbf45e403,0x3f187fc0,0xbf4d9f02,0x3f0e39da,0xbf54db31,0x3f039c3d,0xbf5b941a,0x3ef15aea,0xbf61c598,0x3edae880,0xbf676bd8,
0x3ec3ef15,0xbf6c835e,0x3ea09ae5,0xbf731447,0x3e78cfcc,0xbf7853f8,0x3e2f10a2,0xbf7c3b28,0x3dc8bd36,0xbf7ec46d,0x3cc90ab0,0xbf7fec43,0xbd48fb30,0xbf7fb10f,0xbdfab273,0xbf7e1324,
0x3f226799,0xbf45e403,0x3f173c07,0xbf4e8d90,0x3f0b9a6b,0xbf5695e5,0x3eff17b2,0xbf5df6be,0x3ee63375,0xbf64aa59,0x3ecc9b8b,0xbf6aab7b,0x3eb263ef,0xbf6ff573,0x3e97a117,0xbf748422,
0x3e94a031,0xbf74fa0b,0x3e5a3997,0xbf7a1e84,0x3e09cf86,0xbf7dabcc,0x3d621469,0xbf7f9c18,0xbcc90ab0,0xbf7fec43,0xbdd53db9,0xbf7e9bc9,0xbe3b6ecf,0xbf7baccd,0xbe8586ce,0xbf772417,
0x3f0e39da,0xbf54db31,0x3f00e7e4,0xbf5d2d53,0x3ee63375,0xbf64aa59,0x3ec9b953,0xbf6b4b0c,0x3eac7cd4,0xbf710908,0x3e8e9a22,0xbf75dec6,0x3e605c13,0xbf79c79d,0x3e22abb6,0xbf7cbfc9,
0x3e47c5c2,0xbf7b14be,0x3de1bc2e,0xbf7e70b0,0x3cc90ab0,0xbf7fec43,0xbd7b2b74,0xbf7f84ab,0xbe164083,0xbf7d3aac,0xbe6c9a7f,0xbf791298,0xbea09ae5,0xbf731447,0xbec9b953,0xbf6b4b0c,
0x3ef15aea,0xbf61c598,0x3ed25a09,0xbf696591,0x3eb263ef,0xbf6ff573,0x3e919ddd,0xbf756d97,0x3e605c13,0xbf79c79d,0x3e1c76de,0xbf7cfe73,0x3dafb680,0xbf7f0e58,0x3c96c9b6,0xbf7ff4e6,
0x3dc8bd36,0xbf7ec46d,0x3bc90f88,0xbf7ffec4,0xbdafb680,0xbf7f0e58,0xbe354098,0xbf7bf531,0xbe888e93,0xbf76ba07,0xbeb554ec,0xbf6f6830,0xbee0924f,0xbf660f88,0xbf04f484,0xbf5ac450,
0x0,0xbf800000,0xbdc8bd36,0xbf7ec46d,0xbe47c5c2,0xbf7b14be,0xbe94a031,0xbf74fa0b,0xbec3ef15,0xbf6c835e,0xbef15aea,0xbf61c598,0xbf0e39da,0xbf54db31,0xbf226799,0xbf45e403,
0xbec3ef15,0xbf6c835e,0xbefc5d27,0xbf5ebe05,0xbf187fc0,0xbf4d9f02,0xbf3085bb,0xbf396842,0xbf45e403,0xbf226799,0xbf584853,0xbf08f59b,0xbf676bd8,0xbedae880,0xbf731447,0xbea09ae5,
0xbdc8bd36,0xbf7ec46d,0xbe4dee60,0xbf7ac516,0xbe9aa086,0xbf740bdd,0xbecc9b8b,0xbf6aab7b,0xbefc5d27,0xbf5ebe05,0xbf14b039,0xbf5064af,0xbf299415,0xbf3fc767,0xbf3ca003,0xbf2d1469,
0xbef15aea,0xbf61c598,0xbf14b039,0xbf5064af,0xbf2e3bde,0xbf3b8f3b,0xbf44e3f5,0xbf239da9,0xbf584853,0xbf08f59b,0xbf6816a8,0xbed8106b,0xbf740bdd,0xbe9aa086,0xbf7bf531,0xbe354098,
0xbe47c5c2,0xbf7b14be,0xbe9aa086,0xbf740bdd,0xbecf7bca,0xbf6a09a7,0xbf00e7e4,0xbf5d2d53,0xbf187fc0,0xbf4d9f02,0xbf2e3bde,0xbf3b8f3b,0xbf41d870,0xbf273656,0xbf531849,0xbf10d3cd,
0xbf0e39da,0xbf54db31,0xbf299415,0xbf3fc767,0xbf41d870,0xbf273656,0xbf5695e5,0xbf0b9a6b,0xbf676bd8,0xbedae880,0xbf740bdd,0xbe9aa086,0xbf7c3b28,0xbe2f10a2,0xbf7fd397,0xbd16c32c,
0xbe94a031,0xbf74fa0b,0xbecc9b8b,0xbf6aab7b,0xbf00e7e4,0xbf5d2d53,0xbf19c200,0xbf4cae79,0xbf3085bb,0xbf396842,0xbf44e3f5,0xbf239da9,0xbf5695e5,0xbf0b9a6b,0xbf655e0b,0xbee363fa,
0xbf226799,0xbf45e403,0xbf3ca003,0xbf2d1469,0xbf531849,0xbf10d3cd,0xbf655e0b,0xbee363fa,0xbf731447,0xbea09ae5,0xbf7bf531,0xbe354098,0xbf7fd397,0xbd16c32c,0xbf7e9bc9,0x3dd53db9,
0xbf3504f3,0xbf3504f3,0xbf4d9f02,0xbf187fc0,0xbf61c598,0xbef15aea,0xbf710908,0xbeac7cd4,0xbf7b14be,0xbe47c5c2,0xbf7fb10f,0xbd48fb30,0xbf7ec46d,0x3dc8bd36,0xbf7853f8,0x3e78cfcc,
0xbf6c835e,0xbec3ef15,0xbf79c79d,0xbe605c13,0xbf7fb10f,0xbd48fb30,0xbf7e1324,0x3dfab273,0xbf74fa0b,0x3e94a031,0xbf64aa59,0x3ee63375,0xbf4d9f02,0x3f187fc0,0xbf3085bb,0x3f396842,
0xbf45e403,0xbf226799,0xbf5c61c7,0xbf0242b1,0xbf6db293,0xbebe1d4a,0xbf796e4e,0xbe667c66,0xbf7f4e6d,0xbd96a905,0xbf7f2f9d,0x3da3308c,0xbf791298,0x3e6c9a7f,0xbf6d1c1d,0x3ec1071e,
0xbf74fa0b,0xbe94a031,0xbf7e4323,0xbdee3876,0xbf7f84ab,0x3d7b2b74,0xbf78b47b,0x3e72b651,0xbf6a09a7,0x3ecf7bca,0xbf53fac3,0x3f0f8784,0xbf373a23,0x3f32c8c9,0xbf14b039,0x3f5064af,
0xbf54db31,0xbf0e39da,0xbf68bf3c,0xbed53641,0xbf76ba07,0xbe888e93,0xbf7e70b0,0xbde1bc2e,0xbf7fb10f,0x3d48fb30,0xbf7a7302,0x3e541501,0xbf6ed89e,0x3eb8442a,0xbf5d2d53,0x3f00e7e4,
0xbf7b14be,0xbe47c5c2,0xbf7ffb11,0xbc490e90,0xbf7c3b28,0x3e2f10a2,0xbf6ff573,0x3eb263ef,0xbf5b941a,0x3f039c3d,0xbf3fc767,0x3f299415,0xbf1d7fd1,0x3f49d112,0xbeebcbbb,0x3f633c5a,
0xbf61c598,0xbef15aea,0xbf7294f8,0xbea395c5,0xbf7cbfc9,0xbe22abb6,0xbf7ffec4,0x3bc90f88,0xbf7c3b28,0x3e2f10a2,0xbf718f57,0x3ea986c4,0xbf604621,0x3ef6e0cb,0xbf48d8b3,0x3f1ebc12,
0xbf7ec46d,0xbdc8bd36,0xbf7eea9d,0x3dbc3ac3,0xbf75dec6,0x3e8e9a22,0xbf63f473,0x3ee900b7,0xbf49d112,0x3f1d7fd1,0xbf286605,0x3f40d0da,0xbf00e7e4,0x3f5d2d53,0xbea986c4,0x3f718f57,
0x3f800000,0x0,0x3f800000,0x0,0x3f800000,0x0,0x3f800000,0x0,0x3f800000,0x0,0x3f800000,0x0,0x3f800000,0x0,0x3f800000,0x0,
0x3f54db31,0xbf0e39da,0x3f514d3d,0xbf13682a,0x3f4d9f02,0xbf187fc0,0x3f49d112,0xbf1d7fd1,0x3f45e403,0xbf226799,0x3f41d870,0xbf273656,0x3f3daef9,0xbf2beb4a,0x3f396842,0xbf3085bb,
0x3f7d3aac,0xbe164083,0x3f7cfe73,0xbe1c76de,0x3f7cbfc9,0xbe22abb6,0x3f7c7eb0,0xbe28defc,0x3f7c3b28,0xbe2f10a2,0x3f7bf531,0xbe354098,0x3f7baccd,0xbe3b6ecf,0x3f7b61fc,0xbe419b37,
0x3f3daef9,0xbf2beb4a,0x3f385216,0xbf31a81d,0x3f32c8c9,0xbf373a23,0x3f2d1469,0xbf3ca003,0x3f273656,0xbf41d870,0x3f212ff9,0xbf46e22a,0x3f1b02c6,0xbf4bbbf8,0x3f14b039,0xbf5064af,
0x3f74fa0b,0xbe94a031,0x3f740bdd,0xbe9aa086,0x3f731447,0xbea09ae5,0x3f721352,0xbea68f12,0x3f710908,0xbeac7cd4,0x3f6ff573,0xbeb263ef,0x3f6ed89e,0xbeb8442a,0x3f6db293,0xbebe1d4a,
0x3f226799,0xbf45e403,0x3f1b02c6,0xbf4bbbf8,0x3f13682a,0xbf514d3d,0x3f0b9a6b,0xbf5695e5,0x3f039c3d,0xbf5b941a,0x3ef6e0cb,0xbf604621,0x3ee63375,0xbf64aa59,0x3ed53641,0xbf68bf3c,
0x3f676bd8,0xbedae880,0x3f655e0b,0xbee363fa,0x3f633c5a,0xbeebcbbb,0x3f6106f2,0xbef41f07,0x3f5ebe05,0xbefc5d27,0x3f5c61c7,0xbf0242b1,0x3f59f26a,0xbf064b82,0x3f577026,0xbf0a48ad,
0x3f039c3d,0xbf5b941a,0x3ef41f07,0xbf6106f2,0x3ee0924f,0xbf660f88,0x3ecc9b8b,0xbf6aab7b,0x3eb8442a,0xbf6ed89e,0x3ea395c5,0xbf7294f8,0x3e8e9a22,0xbf75dec6,0x3e72b651,0xbf78b47b,
0x3ec3ef15,0xbf6c835e,0x3eac7cd4,0xbf710908,0x3e94a031,0xbf74fa0b,0x3e78cfcc,0xbf7853f8,0x3e47c5c2,0xbf7b14be,0x3e164083,0xbf7d3aac,0x3dc8bd36,0xbf7ec46d,0x3d48fb30,0xbf7fb10f,
0xbe47c5c2,0xbf7b14be,0xbe888e93,0xbf76ba07,0xbeac7cd4,0xbf710908,0xbecf7bca,0xbf6a09a7,0xbef15aea,0xbf61c598,0xbf08f59b,0xbf584853,0xbf187fc0,0xbf4d9f02,0xbf273656,0xbf41d870,
0x3e78cfcc,0xbf7853f8,0x3e419b37,0xbf7b61fc,0x3e09cf86,0xbf7dabcc,0x3da3308c,0xbf7f2f9d,0x3cc90ab0,0xbf7fec43,0xbcfb49ba,0xbf7fe129,0xbdafb680,0xbf7f0e58,0xbe1008b7,0xbf7d7474,
0xbeac7cd4,0xbf710908,0xbed25a09,0xbf696591,0xbef6e0cb,0xbf604621,0xbf0cead0,0xbf55b993,0xbf1d7fd1,0xbf49d112,0xbf2d1469,0xbf3ca003,0xbf3b8f3b,0xbf2e3bde,0xbf48d8b3,0xbf1ebc12,
0x3dc8bd36,0xbf7ec46d,0x3d16c32c,0xbf7fd397,0xbcc90ab0,0xbf7fec43,0xbdafb680,0xbf7f0e58,0xbe164083,0xbf7d3aac,0xbe541501,0xbf7a7302,0xbe888e93,0xbf76ba07,0xbea68f12,0xbf721352,
0xbef15aea,0xbf61c598,0xbf0b9a6b,0xbf5695e5,0xbf1d7fd1,0xbf49d112,0xbf2e3bde,0xbf3b8f3b,0xbf3daef9,0xbf2beb4a,0xbf4bbbf8,0xbf1b02c6,0xbf584853,0xbf08f59b,0xbf633c5a,0xbeebcbbb,
0xbd48fb30,0xbf7fb10f,0xbdee3876,0xbf7e4323,0xbe3b6ecf,0xbf7baccd,0xbe7ee6e1,0xbf77f110,0xbea09ae5,0xbf731447,0xbec1071e,0xbf6d1c1d,0xbee0924f,0xbf660f88,0xbeff17b2,0xbf5df6be,
0xbf187fc0,0xbf4d9f02,0xbf2ac082,0xbf3ebc1b,0xbf3b8f3b,0xbf2e3bde,0xbf4ac77f,0xbf1c420c,0xbf584853,0xbf08f59b,0xbf63f473,0xbee900b7,0xbf6db293,0xbebe1d4a,0xbf756d97,0xbe919ddd,
0xbf3504f3,0xbf3504f3,0xbf45e403,0xbf226799,0xbf54db31,0xbf0e39da,0xbf61c598,0xbef15aea,0xbf6c835e,0xbec3ef15,0xbf74fa0b,0xbe94a031,0xbf7b14be,0xbe47c5c2,0xbf7ec46d,0xbdc8bd36,
0xbf7b14be,0xbe47c5c2,0xbf7f4e6d,0xbd96a905,0xbf7fb10f,0x3d48fb30,0xbf7c3b28,0x3e2f10a2,0xbf74fa0b,0x3e94a031,0xbf6a09a7,0x3ecf7bca,0xbf5b941a,0x3f039c3d,0xbf49d112,0x3f1d7fd1,
0xbf4d9f02,0xbf187fc0,0xbf5c61c7,0xbf0242b1,0xbf68bf3c,0xbed53641,0xbf7294f8,0xbea395c5,0xbf79c79d,0xbe605c13,0xbf7e4323,0xbdee3876,0xbf7ffb11,0xbc490e90,0xbf7eea9d,0x3dbc3ac3,
0xbf7fb10f,0xbd48fb30,0xbf7f2f9d,0x3da3308c,0xbf7a7302,0x3e541501,0xbf718f57,0x3ea986c4,0xbf64aa59,0x3ee63375,0xbf53fac3,0x3f0f8784,0xbf3fc767,0x3f299415,0xbf286605,0x3f40d0da,
0xbf61c598,0xbef15aea,0xbf6db293,0xbebe1d4a,0xbf76ba07,0xbe888e93,0xbf7cbfc9,0xbe22abb6,0xbf7fb10f,0xbd48fb30,0xbf7f84ab,0x3d7b2b74,0xbf7c3b28,0x3e2f10a2,0xbf75dec6,0x3e8e9a22,
0xbf7ec46d,0x3dc8bd36,0xbf791298,0x3e6c9a7f,0xbf6ed89e,0x3eb8442a,0xbf604621,0x3ef6e0cb,0xbf4d9f02,0x3f187fc0,0xbf373a23,0x3f32c8c9,0xbf1d7fd1,0x3f49d112,0xbf00e7e4,0x3f5d2d53,
0xbf710908,0xbeac7cd4,0xbf796e4e,0xbe667c66,0xbf7e70b0,0xbde1bc2e,0xbf7ffec4,0x3bc90f88,0xbf7e1324,0x3dfab273,0xbf78b47b,0x3e72b651,0xbf6ff573,0x3eb263ef,0xbf63f473,0x3ee900b7,
0xbf7853f8,0x3e78cfcc,0xbf6d1c1d,0x3ec1071e,0xbf5d2d53,0x3f00e7e4,0xbf48d8b3,0x3f1ebc12,0xbf3085bb,0x3f396842,0xbf14b039,0x3f5064af,0xbeebcbbb,0x3f633c5a,0xbea986c4,0x3f718f57,
0xbf6c835e,0x3ec3ef15,0xbf5b941a,0x3f039c3d,0xbf45e403,0x3f226799,0xbf2beb4a,0x3f3daef9,0xbf0e39da,0x3f54db31,0xbedae880,0x3f676bd8,0xbe94a031,0x3f74fa0b,0xbe164083,0x3f7d3aac,
0xbf0e39da,0x3f54db31,0xbecf7bca,0x3f6a09a7,0xbe78cfcc,0x3f7853f8,0xbd96a905,0x3f7f4e6d,0x3dc8bd36,0x3f7ec46d,0x3e888e93,0x3f76ba07,0x3edae880,0x3f676bd8,0x3f13682a,0x3f514d3d,
0xbf5b941a,0x3f039c3d,0xbf44e3f5,0x3f239da9,0xbf299415,0x3f3fc767,0xbf0a48ad,0x3f577026,0xbecf7bca,0x3f6a09a7,0xbe8586ce,0x3f772417,0xbde1bc2e,0x3f7e70b0,0x3d2fe007,0x3f7fc38f,
0xbedae880,0x3f676bd8,0xbe8586ce,0x3f772417,0xbdafb680,0x3f7f0e58,0x3dbc3ac3,0x3f7eea9d,0x3e888e93,0x3f76ba07,0x3eddbe79,0x3f66becc,0x3f15f6d9,0x3f4f7a1f,0x3f385216,0x3f31a81d,
0xbf45e403,0x3f226799,0xbf299415,0x3f3fc767,0xbf08f59b,0x3f584853,0xbec9b953,0x3f6b4b0c,0xbe78cfcc,0x3f7853f8,0xbdafb680,0x3f7f0e58,0x3d96a905,0x3f7f4e6d,0x3e6c9a7f,0x3f791298,
0xbe94a031,0x3f74fa0b,0xbde1bc2e,0x3f7e70b0,0x3d96a905,0x3f7f4e6d,0x3e827dc0,0x3f778bc5,0x3edae880,0x3f676bd8,0x3f15f6d9,0x3f4f7a1f,0x3f396842,0x3f3085bb,0x3f5695e5,0x3f0b9a6b,
0xbf2beb4a,0x3f3daef9,0xbf0a48ad,0x3f577026,0xbec9b953,0x3f6b4b0c,0xbe72b651,0x3f78b47b,0xbd96a905,0x3f7f4e6d,0x3dbc3ac3,0x3f7eea9d,0x3e827dc0,0x3f778bc5,0x3ed25a09,0x3f696591,
0xbe164083,0x3f7d3aac,0x3d2fe007,0x3f7fc38f,0x3e6c9a7f,0x3f791298,0x3ed25a09,0x3f696591,0x3f13682a,0x3f514d3d,0x3f385216,0x3f31a81d,0x3f5695e5,0x3f0b9a6b,0x3f6d1c1d,0x3ec1071e,
0x3e00,0x3e00,0x3e00,0x3e00,0x3e00,0x3e00,0x3e00,0x3e00,0x3e00,0x3e00,0x3e00,0x3e00,0x3e00,0x3e00,0x3e00,0x3e00,
0xbd443ded,0xbcc83dfb,0xbc493dff,0xbd153df5,0xbdb53db5,0xbdd53d8e,0xbdc63da2,0xbde23d71,0xbe000000,0xbdfbbcc8,0xbdffbc49,0xbdf5bd15,0xbdb5bdb5,0xbd8ebdd5,0xbda2bdc6,0xbd71bde2,
0xbdb53db5,0xbd443ded,0xbcc83dfb,0xbd8e3dd5,0xbe000000,0xbdedbd44,0xbdfbbcc8,0xbdd5bd8e,0xbe00,0x3d44bded,0x3cc8bdfb,0x3d8ebdd5,0x3e000000,0x3ded3d44,0x3dfb3cc8,0x3dd53d8e,
0xbded3d44,0xbd8e3dd5,0xbd153df5,0xbdc63da2,0xbdb5bdb5,0xbcc8bdfb,0xbd71bde2,0x3c49bdff,0x3e000000,0x3dd53d8e,0x3df53d15,0x3da23dc6,0xbdb53db5,0xbdfb3cc8,0xbde23d71,0xbdffbc49,
0xbe000000,0xbdb53db5,0xbd443ded,0xbded3d44,0xbe00,0x3db5bdb5,0x3d44bded,0x3dedbd44,0x3e00,0xbdb53db5,0xbd443ded,0xbded3d44,0xbe00,0x3db5bdb5,0x3d44bded,0x3dedbd44,
0xbdedbd44,0xbdd53d8e,0xbd713de2,0xbdff3c49,0x3db5bdb5,0x3dfb3cc8,0x3df5bd15,0x3dc63da2,0xbe000000,0xbd8ebdd5,0xbde2bd71,0xbc49bdff,0x3db53db5,0xbcc83dfb,0x3d153df5,0xbda23dc6,
0xbdb5bdb5,0xbded3d44,0xbd8e3dd5,0xbdfbbcc8,0x3e000000,0x3d443ded,0x3dd53d8e,0xbcc83dfb,0xbe00,0x3dedbd44,0x3d8ebdd5,0x3dfb3cc8,0xbe000000,0xbd44bded,0xbdd5bd8e,0x3cc8bdfb,
0xbd44bded,0xbdfb3cc8,0xbda23dc6,0xbde2bd71,0x3db53db5,0xbd8e3dd5,0x3c493dff,0xbdf53d15,0x3e000000,0x3cc83dfb,0x3dc63da2,0xbd713de2,0x3db5bdb5,0x3dd53d8e,0x3dffbc49,0x3d153df5,
0xbe00,0xbe000000,0xbdb53db5,0xbdb5bdb5,0x3e00,0xbe000000,0xbdb53db5,0xbdb5bdb5,0x3e00,0xbe000000,0xbdb53db5,0xbdb5bdb5,0x3e00,0xbe000000,0xbdb53db5,0xbdb5bdb5,
0x3d44bded,0xbdfbbcc8,0xbdc63da2,0xbd71bde2,0xbdb53db5,0xbd8ebdd5,0xbdffbc49,0x3d15bdf5,0xbe000000,0x3cc8bdfb,0xbda2bdc6,0x3de2bd71,0xbdb5bdb5,0x3dd5bd8e,0x3c49bdff,0x3df53d15,
0x3db5bdb5,0xbdedbd44,0xbdd53d8e,0xbcc8bdfb,0xbe000000,0x3d44bded,0xbd8ebdd5,0x3dfbbcc8,0xbe00,0x3ded3d44,0x3dd5bd8e,0x3cc83dfb,0x3e000000,0xbd443ded,0x3d8e3dd5,0xbdfb3cc8,
0x3dedbd44,0xbdd5bd8e,0xbde23d71,0x3c49bdff,0xbdb5bdb5,0x3dfbbcc8,0x3d15bdf5,0x3da23dc6,0x3e000000,0xbd8e3dd5,0x3d713de2,0xbdffbc49,0xbdb53db5,0xbcc8bdfb,0xbdf5bd15,0x3dc6bda2,
0x3e000000,0xbdb5bdb5,0xbded3d44,0x3d44bded,0xbe00,0x3db53db5,0x3dedbd44,0xbd443ded,0x3e00,0xbdb5bdb5,0xbded3d44,0x3d44bded,0xbe00,0x3db53db5,0x3dedbd44,0xbd443ded,
0x3ded3d44,0xbd8ebdd5,0xbdf53d15,0x3da2bdc6,0x3db5bdb5,0xbcc83dfb,0x3de23d71,0xbdff3c49,0xbe000000,0x3dd5bd8e,0xbd15bdf5,0x3dc63da2,0x3db53db5,0xbdfbbcc8,0xbd713de2,0xbc49bdff,
0x3db53db5,0xbd44bded,0xbdfb3cc8,0x3dd5bd8e,0x3e000000,0xbded3d44,0x3cc83dfb,0xbd8ebdd5,0xbe00,0x3d443ded,0x3dfbbcc8,0xbdd53d8e,0xbe000000,0x3dedbd44,0xbcc8bdfb,0x3d8e3dd5,
0x3d443ded,0xbcc8bdfb,0xbdff3c49,0x3df5bd15,0x3db53db5,0xbdd5bd8e,0xbda23dc6,0x3d71bde2,0x3e000000,0xbdfb3cc8,0x3c493dff,0xbd15bdf5,0x3db5bdb5,0xbd8e3dd5,0x3dc63da2,0xbde2bd71,
0x3e00,0xbe00,0xbe000000,0x3e000000,0x3e00,0xbe00,0xbe000000,0x3e000000,0x3e00,0xbe00,0xbe000000,0x3e000000,0x3e00,0xbe00,0xbe000000,0x3e000000,
0xbd443ded,0x3cc8bdfb,0xbdffbc49,0x3df53d15,0xbdb53db5,0x3dd5bd8e,0xbda2bdc6,0x3d713de2,0xbe000000,0x3dfb3cc8,0x3c49bdff,0xbd153df5,0xbdb5bdb5,0x3d8e3dd5,0x3dc6bda2,0xbde23d71,
0xbdb53db5,0x3d44bded,0xbdfbbcc8,0x3dd53d8e,0xbe000000,0x3ded3d44,0x3cc8bdfb,0xbd8e3dd5,0xbe00,0xbd443ded,0x3dfb3cc8,0xbdd5bd8e,0x3e000000,0xbdedbd44,0xbcc83dfb,0x3d8ebdd5,
0xbded3d44,0x3d8ebdd5,0xbdf5bd15,0x3da23dc6,0xbdb5bdb5,0x3cc83dfb,0x3de2bd71,0xbdffbc49,0x3e000000,0xbdd5bd8e,0xbd153df5,0x3dc6bda2,0xbdb53db5,0x3dfbbcc8,0xbd71bde2,0xbc493dff,
0xbe000000,0x3db5bdb5,0xbdedbd44,0x3d443ded,0xbe00,0xbdb53db5,0x3ded3d44,0xbd44bded,0x3e00,0x3db5bdb5,0xbdedbd44,0x3d443ded,0xbe00,0xbdb53db5,0x3ded3d44,0xbd44bded,
0xbdedbd44,0x3dd5bd8e,0xbde2bd71,0x3c493dff,0x3db5bdb5,0xbdfbbcc8,0x3d153df5,0x3da2bdc6,0xbe000000,0x3d8e3dd5,0x3d71bde2,0xbdff3c49,0x3db53db5,0x3cc8bdfb,0xbdf53d15,0x3dc63da2,
0xbdb5bdb5,0x3dedbd44,0xbdd5bd8e,0xbcc83dfb,0x3e000000,0xbd44bded,0xbd8e3dd5,0x3dfb3cc8,0xbe00,0xbded3d44,0x3dd53d8e,0x3cc8bdfb,0xbe000000,0x3d443ded,0x3d8ebdd5,0xbdfbbcc8,
0xbd44bded,0x3dfbbcc8,0xbdc6bda2,0xbd713de2,0x3db53db5,0x3d8ebdd5,0xbdff3c49,0x3d153df5,0x3e000000,0xbcc8bdfb,0xbda23dc6,0x3de23d71,0x3db5bdb5,0xbdd5bd8e,0x3c493dff,0x3df5bd15,
0xbe00,0x3e000000,0xbdb5bdb5,0xbdb53db5,0x3e00,0x3e000000,0xbdb5bdb5,0xbdb53db5,0x3e00,0x3e000000,0xbdb5bdb5,0xbdb53db5,0x3e00,0x3e000000,0xbdb5bdb5,0xbdb53db5,
0x3d44bded,0x3dfb3cc8,0xbda2bdc6,0xbde23d71,0xbdb53db5,0x3d8e3dd5,0x3c49bdff,0xbdf5bd15,0xbe000000,0xbcc83dfb,0x3dc6bda2,0xbd71bde2,0xbdb5bdb5,0xbdd53d8e,0x3dff3c49,0x3d15bdf5,
0x3db5bdb5,0x3ded3d44,0xbd8ebdd5,0xbdfb3cc8,0xbe000000,0xbd443ded,0x3dd5bd8e,0xbcc8bdfb,0xbe00,0xbdedbd44,0x3d8e3dd5,0x3dfbbcc8,0x3e000000,0x3d44bded,0xbdd53d8e,0x3cc83dfb,
0x3dedbd44,0x3dd53d8e,0xbd71bde2,0xbdffbc49,0xbdb5bdb5,0xbdfb3cc8,0x3df53d15,0x3dc6bda2,0x3e000000,0x3d8ebdd5,0xbde23d71,0xbc493dff,0xbdb53db5,0x3cc83dfb,0x3d15bdf5,0xbda2bdc6,
0x3e000000,0x3db53db5,0xbd44bded,0xbdedbd44,0xbe00,0xbdb5bdb5,0x3d443ded,0x3ded3d44,0x3e00,0x3db53db5,0xbd44bded,0xbdedbd44,0xbe00,0xbdb5bdb5,0x3d443ded,0x3ded3d44,
0x3ded3d44,0x3d8e3dd5,0xbd15bdf5,0xbdc6bda2,0x3db5bdb5,0x3cc8bdfb,0xbd713de2,0x3c493dff,0xbe000000,0xbdd53d8e,0x3df5bd15,0x3da2bdc6,0x3db53db5,0x3dfb3cc8,0xbde2bd71,0xbdff3c49,
0x3db53db5,0x3d443ded,0xbcc8bdfb,0xbd8ebdd5,0x3e000000,0x3dedbd44,0xbdfb3cc8,0xbdd53d8e,0xbe00,0xbd44bded,0x3cc83dfb,0x3d8e3dd5,0xbe000000,0xbded3d44,0x3dfbbcc8,0x3dd5bd8e,
0x3d443ded,0x3cc83dfb,0xbc49bdff,0xbd15bdf5,0x3db53db5,0x3dd53d8e,0xbdc6bda2,0xbde2bd71,0x3e000000,0x3dfbbcc8,0xbdff3c49,0xbdf53d15,0x3db5bdb5,0x3d8ebdd5,0xbda23dc6,0xbd713de2,
0x3d803d80,0x3e00,0x3e00,0x3e00,0x3e00,0x3e00,0x3e00,0x3e00,0x3e00,0x3e00,0x3e00,0x3e00,0x3e00,0x3e00,0x3e00,0x3e00,
0xbd803d80,0x3cc8bdfb,0x3c49bdff,0x3d15bdf5,0xbded3d44,0x3dd5bd8e,0x3dc6bda2,0x3de2bd71,0xbdedbd44,0x3dfb3cc8,0x3dff3c49,0x3df53d15,0xbd44bded,0x3d8e3dd5,0x3da23dc6,0x3d713de2,
0x3d803d80,0xbd443ded,0xbcc83dfb,0xbd8e3dd5,0xbdb5bdb5,0xbdedbd44,0xbdfbbcc8,0xbdd5bd8e,0x3db5bdb5,0x3d44bded,0x3cc8bdfb,0x3d8ebdd5,0x3db53db5,0x3ded3d44,0x3dfb3cc8,0x3dd53d8e,
0xbd803d80,0x3d8ebdd5,0x3d15bdf5,0x3dc6bda2,0x3d44bded,0x3cc83dfb,0x3d713de2,0xbc493dff,0x3d443ded,0xbdd5bd8e,0xbdf5bd15,0xbda2bdc6,0xbdedbd44,0x3dfbbcc8,0x3de2bd71,0x3dff3c49,
0x3d803d80,0xbdb53db5,0xbd443ded,0xbded3d44,0x3e000000,0x3db5bdb5,0x3d44bded,0x3dedbd44,0xbe000000,0xbdb53db5,0xbd443ded,0xbded3d44,0x3e000000,0x3db5bdb5,0x3d44bded,0x3dedbd44,
0xbd803d80,0x3dd5bd8e,0x3d71bde2,0x3dffbc49,0x3d443ded,0xbdfbbcc8,0xbdf53d15,0xbdc6bda2,0x3d44bded,0x3d8e3dd5,0x3de23d71,0x3c493dff,0xbded3d44,0x3cc8bdfb,0xbd15bdf5,0x3da2bdc6,
0x3d803d80,0xbded3d44,0xbd8e3dd5,0xbdfbbcc8,0xbdb53db5,0x3d443ded,0x3dd53d8e,0xbcc83dfb,0x3db53db5,0x3dedbd44,0x3d8ebdd5,0x3dfb3cc8,0x3db5bdb5,0xbd44bded,0xbdd5bd8e,0x3cc8bdfb,
0xbd803d80,0x3dfbbcc8,0x3da2bdc6,0x3de23d71,0xbdedbd44,0x3d8ebdd5,0xbc49bdff,0x3df5bd15,0xbded3d44,0xbcc8bdfb,0xbdc6bda2,0x3d71bde2,0xbd443ded,0xbdd5bd8e,0xbdff3c49,0xbd15bdf5,
0x3d803d80,0xbe000000,0xbdb53db5,0xbdb5bdb5,0xbe00,0xbe000000,0xbdb53db5,0xbdb5bdb5,0xbe00,0xbe000000,0xbdb53db5,0xbdb5bdb5,0xbe00,0xbe000000,0xbdb53db5,0xbdb5bdb5,
0xbd803d80,0x3dfb3cc8,0x3dc6bda2,0x3d713de2,0x3dedbd44,0x3d8e3dd5,0x3dff3c49,0xbd153df5,0x3ded3d44,0xbcc83dfb,0x3da23dc6,0xbde23d71,0x3d443ded,0xbdd53d8e,0xbc493dff,0xbdf5bd15,
0x3d803d80,0xbdedbd44,0xbdd53d8e,0xbcc8bdfb,0x3db53db5,0x3d44bded,0xbd8ebdd5,0x3dfbbcc8,0xbdb53db5,0x3ded3d44,0x3dd5bd8e,0x3cc83dfb,0xbdb5bdb5,0xbd443ded,0x3d8e3dd5,0xbdfb3cc8,
0xbd803d80,0x3dd53d8e,0x3de2bd71,0xbc493dff,0xbd443ded,0xbdfb3cc8,0xbd153df5,0xbda2bdc6,0xbd44bded,0x3d8ebdd5,0xbd71bde2,0x3dff3c49,0x3ded3d44,0x3cc83dfb,0x3df53d15,0xbdc63da2,
0x3d803d80,0xbdb5bdb5,0xbded3d44,0x3d44bded,0xbe000000,0x3db53db5,0x3dedbd44,0xbd443ded,0x3e000000,0xbdb5bdb5,0xbded3d44,0x3d44bded,0xbe000000,0x3db53db5,0x3dedbd44,0xbd443ded,
0xbd803d80,0x3d8e3dd5,0x3df5bd15,0xbda23dc6,0xbd44bded,0x3cc8bdfb,0xbde2bd71,0x3dffbc49,0xbd443ded,0xbdd53d8e,0x3d153df5,0xbdc6bda2,0x3dedbd44,0x3dfb3cc8,0x3d71bde2,0x3c493dff,
0x3d803d80,0xbd44bded,0xbdfb3cc8,0x3dd5bd8e,0x3db5bdb5,0xbded3d44,0x3cc83dfb,0xbd8ebdd5,0xbdb5bdb5,0x3d443ded,0x3dfbbcc8,0xbdd53d8e,0xbdb53db5,0x3dedbd44,0xbcc8bdfb,0x3d8e3dd5,
0xbd803d80,0x3cc83dfb,0x3dffbc49,0xbdf53d15,0x3ded3d44,0x3dd53d8e,0x3da2bdc6,0xbd713de2,0x3dedbd44,0x3dfbbcc8,0xbc49bdff,0x3d153df5,0x3d44bded,0x3d8ebdd5,0xbdc6bda2,0x3de23d71,
0x3d803d80,0xbe00,0xbe000000,0x3e000000,0x3e00,0xbe00,0xbe000000,0x3e000000,0x3e00,0xbe00,0xbe000000,0x3e000000,0x3e00,0xbe00,0xbe000000,0x3e000000,
0xbd803d80,0xbcc83dfb,0x3dff3c49,0xbdf5bd15,0xbded3d44,0xbdd53d8e,0x3da23dc6,0xbd71bde2,0xbdedbd44,0xbdfbbcc8,0xbc493dff,0x3d15bdf5,0xbd44bded,0xbd8ebdd5,0xbdc63da2,0x3de2bd71,
0x3d803d80,0x3d44bded,0xbdfbbcc8,0x3dd53d8e,0xbdb5bdb5,0x3ded3d44,0x3cc8bdfb,0xbd8e3dd5,0x3db5bdb5,0xbd443ded,0x3dfb3cc8,0xbdd5bd8e,0x3db53db5,0xbdedbd44,0xbcc83dfb,0x3d8ebdd5,
0xbd803d80,0xbd8e3dd5,0x3df53d15,0xbda2bdc6,0x3d44bded,0xbcc8bdfb,0xbde23d71,0x3dff3c49,0x3d443ded,0x3dd53d8e,0x3d15bdf5,0xbdc63da2,0xbdedbd44,0xbdfb3cc8,0x3d713de2,0x3c49bdff,
0x3d803d80,0x3db5bdb5,0xbdedbd44,0x3d443ded,0x3e000000,0xbdb53db5,0x3ded3d44,0xbd44bded,0xbe000000,0x3db5bdb5,0xbdedbd44,0x3d443ded,0x3e000000,0xbdb53db5,0x3ded3d44,0xbd44bded,
0xbd803d80,0xbdd53d8e,0x3de23d71,0xbc49bdff,0x3d443ded,0x3dfb3cc8,0xbd15bdf5,0xbda23dc6,0x3d44bded,0xbd8ebdd5,0xbd713de2,0x3dffbc49,0xbded3d44,0xbcc83dfb,0x3df5bd15,0xbdc6bda2,
0x3d803d80,0x3dedbd44,0xbdd5bd8e,0xbcc83dfb,0xbdb53db5,0xbd44bded,0xbd8e3dd5,0x3dfb3cc8,0x3db53db5,0xbded3d44,0x3dd53d8e,0x3cc8bdfb,0x3db5bdb5,0x3d443ded,0x3d8ebdd5,0xbdfbbcc8,
0xbd803d80,0xbdfb3cc8,0x3dc63da2,0x3d71bde2,0xbdedbd44,0xbd8e3dd5,0x3dffbc49,0xbd15bdf5,0xbded3d44,0x3cc83dfb,0x3da2bdc6,0xbde2bd71,0xbd443ded,0x3dd53d8e,0xbc49bdff,0xbdf53d15,
0x3d803d80,0x3e000000,0xbdb5bdb5,0xbdb53db5,0xbe00,0x3e000000,0xbdb5bdb5,0xbdb53db5,0xbe00,0x3e000000,0xbdb5bdb5,0xbdb53db5,0xbe00,0x3e000000,0xbdb5bdb5,0xbdb53db5,
0xbd803d80,0xbdfbbcc8,0x3da23dc6,0x3de2bd71,0x3dedbd44,0xbd8ebdd5,0xbc493dff,0x3df53d15,0x3ded3d44,0x3cc8bdfb,0xbdc63da2,0x3d713de2,0x3d443ded,0x3dd5bd8e,0xbdffbc49,0xbd153df5,
0x3d803d80,0x3ded3d44,0xbd8ebdd5,0xbdfb3cc8,0x3db53db5,0xbd443ded,0x3dd5bd8e,0xbcc8bdfb,0xbdb53db5,0xbdedbd44,0x3d8e3dd5,0x3dfbbcc8,0xbdb5bdb5,0x3d44bded,0xbdd53d8e,0x3cc83dfb,
0xbd803d80,0xbdd5bd8e,0x3d713de2,0x3dff3c49,0xbd443ded,0x3dfbbcc8,0xbdf5bd15,0xbdc63da2,0xbd44bded,0xbd8e3dd5,0x3de2bd71,0x3c49bdff,0x3ded3d44,0xbcc8bdfb,0xbd153df5,0x3da23dc6,
0x3d803d80,0x3db53db5,0xbd44bded,0xbdedbd44,0xbe000000,0xbdb5bdb5,0x3d443ded,0x3ded3d44,0x3e000000,0x3db53db5,0xbd44bded,0xbdedbd44,0xbe000000,0xbdb5bdb5,0x3d443ded,0x3ded3d44,
0xbd803d80,0xbd8ebdd5,0x3d153df5,0x3dc63da2,0xbd44bded,0xbcc83dfb,0x3d71bde2,0xbc49bdff,0xbd443ded,0x3dd5bd8e,0xbdf53d15,0xbda23dc6,0x3dedbd44,0xbdfbbcc8,0x3de23d71,0x3dffbc49,
0x3d803d80,0x3d443ded,0xbcc8bdfb,0xbd8ebdd5,0x3db5bdb5,0x3dedbd44,0xbdfb3cc8,0xbdd53d8e,0xbdb5bdb5,0xbd44bded,0x3cc83dfb,0x3d8e3dd5,0xbdb53db5,0xbded3d44,0x3dfbbcc8,0x3dd5bd8e,
0xbd803d80,0xbcc8bdfb,0x3c493dff,0x3d153df5,0x3ded3d44,0xbdd5bd8e,0x3dc63da2,0x3de23d71,0x3dedbd44,0xbdfb3cc8,0x3dffbc49,0x3df5bd15,0x3d44bded,0xbd8e3dd5,0x3da2bdc6,0x3d71bde2,
0xbc493dff,0xbbc93e00,0xbb493e00,0xbc173dff,0xbcc83dfb,0xbcf93df8,0xbce03dfa,0xbd093df7,0xbd443ded,0xbd5b3de7,0xbd4f3dea,0xbd663de5,0xbd8e3dd5,0xbd983dce,0xbd933dd1,0xbd9d3dca,
0xbd713de2,0xbcf93df8,0xbc7b3dfe,0xbd383def,0xbdd53d8e,0xbdf13d2c,0xbde53d66,0xbdfa3ce0,0xbdedbd44,0xbdcebd98,0xbddfbd7c,0xbdb9bdb1,0xbcc8bdfb,0x3bc9be00,0xbc17bdff,0x3cafbdfc,
0xbdc63da2,0xbd5b3de7,0xbce03dfa,0xbd9d3dca,0xbdfbbcc8,0xbdcebd98,0xbdeabd4f,0xbda7bdc2,0x3d44bded,0x3dbebdac,0x3d93bdd1,0x3ddfbd7c,0x3dd53d8e,0x3d843ddc,0x3db13db9,0x3d213df3,
0xbdf53d15,0xbd983dce,0xbd213df3,0xbdd13d93,0xbd8ebdd5,0x3bc9be00,0xbd09bdf7,0x3d38bdef,0x3ded3d44,0x3d843ddc,0x3dc23da7,0x3ce03dfa,0xbdfb3cc8,0xbde7bd5b,0xbdfebc7b,0xbdb9bdb1,
0xbdffbc49,0xbdbe3dac,0xbd4f3dea,0xbdf33d21,0x3cc8bdfb,0x3ddcbd84,0x3d93bdd1,0x3dfebc7b,0xbd443ded,0xbdf13d2c,0xbdb93db1,0xbdffbc17,0x3d8ebdd5,0x3dfdbc96,0x3dd8bd89,0x3df73d09,
0xbde2bd71,0xbddc3d84,0xbd7c3ddf,0xbe003b49,0x3dd5bd8e,0x3de73d5b,0x3dffbc17,0x3d933dd1,0xbdedbd44,0xbc96bdfd,0xbd9dbdca,0x3d38bdef,0x3cc83dfb,0xbdbe3dac,0xbd213df3,0xbdfa3ce0,
0xbda2bdc6,0xbdf13d2c,0xbd933dd1,0xbdf7bd09,0x3dfb3cc8,0x3c963dfd,0x3db13db9,0xbd663de5,0x3d44bded,0x3e003bc9,0x3dd8bd89,0x3dca3d9d,0xbdd5bd8e,0x3cf9bdf8,0xbd38bdef,0x3dc2bda7,
0xbd15bdf5,0xbdfd3c96,0xbda73dc2,0xbdd8bd89,0x3d8e3dd5,0xbdbe3dac,0xbc7b3dfe,0xbe003b49,0x3ded3d44,0xbcf93df8,0x3d663de5,0xbdd13d93,0x3dfbbcc8,0x3d2c3df1,0x3ddf3d7c,0xbd383def,
0x3c49bdff,0xbe00bbc9,0xbdb93db1,0xbda7bdc2,0xbcc83dfb,0xbdf8bcf9,0xbdd83d89,0xbd7cbddf,0xbd443ded,0xbde7bd5b,0xbdef3d38,0xbd21bdf3,0xbd8e3dd5,0xbdcebd98,0xbdfc3caf,0xbc7bbdfe,
0x3d71bde2,0xbdf8bcf9,0xbdca3d9d,0xbd4fbdea,0xbdd53d8e,0xbd2cbdf1,0xbdf3bd21,0x3d89bdd8,0xbdedbd44,0x3d98bdce,0xbd09bdf7,0x3e00bb49,0xbcc8bdfb,0x3e003bc9,0x3da7bdc2,0x3d933dd1,
0x3dc6bda2,0xbde7bd5b,0xbdd83d89,0xbc7bbdfe,0xbdfbbcc8,0x3d98bdce,0xbd38bdef,0x3dff3c17,0x3d44bded,0x3dac3dbe,0x3dfcbcaf,0xbd093df7,0x3dd53d8e,0xbddc3d84,0xbb493e00,0xbde5bd66,
0x3df5bd15,0xbdcebd98,0xbde53d66,0x3cafbdfc,0xbd8ebdd5,0x3e003bc9,0x3d7cbddf,0x3d4f3dea,0x3ded3d44,0xbddc3d84,0x3c173dff,0xbdd8bd89,0xbdfb3cc8,0x3d5bbde7,0xbd9dbdca,0x3e00bb49,
0x3dff3c49,0xbdacbdbe,0xbdef3d38,0x3d66bde5,0x3cc8bdfb,0x3d843ddc,0x3dfcbcaf,0xbd9d3dca,0xbd443ded,0xbd2cbdf1,0xbe00bb49,0x3dc2bda7,0x3d8ebdd5,0x3c963dfd,0x3dfa3ce0,0xbddf3d7c,
0x3de23d71,0xbd84bddc,0xbdf73d09,0x3db1bdb9,0x3dd5bd8e,0xbd5b3de7,0x3dc23da7,0xbdfcbcaf,0xbdedbd44,0x3dfdbc96,0x3c7bbdfe,0x3d4f3dea,0x3cc83dfb,0xbdacbdbe,0xbde53d66,0x3d89bdd8,
0x3da23dc6,0xbd2cbdf1,0xbdfc3caf,0x3ddfbd7c,0x3dfb3cc8,0xbdfd3c96,0xbb493e00,0xbd21bdf3,0x3d44bded,0xbbc93e00,0x3dfa3ce0,0xbdfe3c7b,0xbdd5bd8e,0x3df83cf9,0x3d4fbdea,0xbc173dff,
0x3d153df5,0xbc96bdfd,0xbdff3c17,0x3dfabce0,0x3d8e3dd5,0xbdacbdbe,0xbdca3d9d,0x3db1bdb9,0x3ded3d44,0xbdf8bcf9,0xbd213df3,0x3cafbdfc,0x3dfbbcc8,0xbdf13d2c,0x3d093df7,0xbd4fbdea,
0xbc493dff,0x3bc9be00,0xbe00bb49,0x3dff3c17,0xbcc83dfb,0x3cf9bdf8,0xbdfabce0,0x3df73d09,0xbd443ded,0x3d5bbde7,0xbdeabd4f,0x3de53d66,0xbd8e3dd5,0x3d98bdce,0xbdd1bd93,0x3dca3d9d,
0xbd713de2,0x3cf9bdf8,0xbdfebc7b,0x3def3d38,0xbdd53d8e,0x3df1bd2c,0xbd66bde5,0x3ce03dfa,0xbdedbd44,0x3dce3d98,0x3d7cbddf,0xbdb13db9,0xbcc8bdfb,0xbbc93e00,0x3dffbc17,0xbdfcbcaf,
0xbdc63da2,0x3d5bbde7,0xbdfabce0,0x3dca3d9d,0xbdfbbcc8,0x3dce3d98,0x3d4fbdea,0xbdc23da7,0x3d44bded,0xbdbe3dac,0x3dd13d93,0xbd7cbddf,0x3dd53d8e,0xbd84bddc,0xbdb93db1,0x3df3bd21,
0xbdf53d15,0x3d98bdce,0xbdf3bd21,0x3d933dd1,0xbd8ebdd5,0xbbc93e00,0x3df7bd09,0xbdefbd38,0x3ded3d44,0xbd84bddc,0xbda73dc2,0x3dfabce0,0xbdfb3cc8,0x3de73d5b,0x3c7bbdfe,0xbdb13db9,
0xbdffbc49,0x3dbebdac,0xbdeabd4f,0x3d213df3,0x3cc8bdfb,0xbddc3d84,0x3dd13d93,0xbc7bbdfe,0xbd443ded,0x3df1bd2c,0xbdb1bdb9,0xbc173dff,0x3d8ebdd5,0xbdfd3c96,0x3d893dd8,0x3d09bdf7,
0xbde2bd71,0x3ddcbd84,0xbddfbd7c,0x3b493e00,0x3dd5bd8e,0xbde7bd5b,0x3c173dff,0x3dd1bd93,0xbdedbd44,0x3c963dfd,0x3dcabd9d,0xbdefbd38,0x3cc83dfb,0x3dbebdac,0xbdf3bd21,0x3ce03dfa,
0xbda2bdc6,0x3df1bd2c,0xbdd1bd93,0xbd093df7,0x3dfb3cc8,0xbc96bdfd,0xbdb93db1,0x3de53d66,0x3d44bded,0xbe00bbc9,0x3d893dd8,0x3d9dbdca,0xbdd5bd8e,0xbcf93df8,0x3defbd38,0xbda7bdc2,
0xbd15bdf5,0x3dfdbc96,0xbdc2bda7,0xbd893dd8,0x3d8e3dd5,0x3dbebdac,0xbdfebc7b,0x3b493e00,0x3ded3d44,0x3cf9bdf8,0xbde53d66,0x3d933dd1,0x3dfbbcc8,0xbd2cbdf1,0xbd7c3ddf,0x3def3d38,
0x3c49bdff,0x3e003bc9,0xbdb1bdb9,0xbdc23da7,0xbcc83dfb,0x3df83cf9,0xbd89bdd8,0xbddf3d7c,0xbd443ded,0x3de73d5b,0xbd38bdef,0xbdf33d21,0xbd8e3dd5,0x3dce3d98,0xbcafbdfc,0xbdfe3c7b,
0x3d71bde2,0x3df83cf9,0xbd9dbdca,0xbdea3d4f,0xbdd53d8e,0x3d2c3df1,0x3d21bdf3,0xbdd8bd89,0xbdedbd44,0xbd983dce,0x3df7bd09,0xbb49be00,0xbcc8bdfb,0xbe00bbc9,0x3dc23da7,0x3dd1bd93,
0x3dc6bda2,0x3de73d5b,0xbd89bdd8,0xbdfe3c7b,0xbdfbbcc8,0xbd983dce,0x3defbd38,0x3c17bdff,0x3d44bded,0xbdacbdbe,0x3caf3dfc,0x3df73d09,0x3dd53d8e,0x3ddcbd84,0xbe00bb49,0xbd663de5,
0x3df5bd15,0x3dce3d98,0xbd66bde5,0xbdfcbcaf,0xbd8ebdd5,0xbe00bbc9,0x3ddf3d7c,0x3deabd4f,0x3ded3d44,0x3ddcbd84,0xbdff3c17,0xbd893dd8,0xbdfb3cc8,0xbd5b3de7,0x3dcabd9d,0xbb49be00,
0x3dff3c49,0x3dac3dbe,0xbd38bdef,0xbde5bd66,0x3cc8bdfb,0xbd84bddc,0x3caf3dfc,0x3dca3d9d,0xbd443ded,0x3d2c3df1,0x3b49be00,0xbda7bdc2,0x3d8ebdd5,0xbc96bdfd,0xbce03dfa,0x3d7c3ddf,
0x3de23d71,0x3d843ddc,0xbd09bdf7,0xbdb9bdb1,0x3dd5bd8e,0x3d5bbde7,0xbda73dc2,0xbcaf3dfc,0xbdedbd44,0xbdfd3c96,0x3dfe3c7b,0x3deabd4f,0x3cc83dfb,0x3dac3dbe,0xbd66bde5,0xbdd8bd89,
0x3da23dc6,0x3d2c3df1,0xbcafbdfc,0xbd7cbddf,0x3dfb3cc8,0x3dfdbc96,0xbe00bb49,0xbdf33d21,0x3d44bded,0x3bc9be00,0xbce03dfa,0x3c7b3dfe,0xbdd5bd8e,0xbdf8bcf9,0x3dea3d4f,0x3dff3c17,
0x3d153df5,0x3c963dfd,0xbc17bdff,0xbce0bdfa,0x3d8e3dd5,0x3dac3dbe,0xbd9dbdca,0xbdb9bdb1,0x3ded3d44,0x3df83cf9,0xbdf3bd21,0xbdfcbcaf,0x3dfbbcc8,0x3df1bd2c,0xbdf73d09,0xbdea3d4f,
0xbdb53d80,0xbdbe3dac,0xbdb93db1,0xbdc23da7,0xbd153df5,0xbddc3d84,0xbdd83d89,0xbddf3d7c,0xbd713de2,0xbdf13d2c,0xbdef3d38,0xbdf33d21,0xbda23dc6,0xbdfd3c96,0xbdfc3caf,0xbdfe3c7b,
0x3db53d80,0x3ddcbd84,0x3dcabd9d,0x3deabd4f,0xbdff3c49,0x3de73d5b,0x3df33d21,0x3dd83d89,0xbda2bdc6,0x3c963dfd,0x3d093df7,0x3b493e00,0x3d15bdf5,0xbdbe3dac,0xbda73dc2,0xbdd13d93,
0xbdb53d80,0xbdf13d2c,0xbdd83d89,0xbdfe3c7b,0xbd71bde2,0xbc96bdfd,0xbd38bdef,0x3c17bdff,0x3df5bd15,0x3e003bc9,0x3dfcbcaf,0x3df73d09,0x3c493dff,0xbcf93df8,0xbb493e00,0xbd663de5,
0x3db53d80,0x3dfdbc96,0x3de5bd66,0x3dfc3caf,0x3da2bdc6,0xbdbe3dac,0xbd7c3ddf,0xbdea3d4f,0xbc493dff,0x3cf9bdf8,0xbc17bdff,0x3d89bdd8,0xbd71bde2,0x3d2c3df1,0x3d9d3dca,0x3b493e00,
0xbdb53d80,0xbe00bbc9,0xbdef3d38,0xbde5bd66,0x3df53d15,0x3df83cf9,0x3dfcbcaf,0x3dca3d9d,0xbde2bd71,0xbde7bd5b,0xbe00bb49,0xbda7bdc2,0x3dc63da2,0x3dce3d98,0x3dfa3ce0,0x3d7c3ddf,
0x3db53d80,0x3df83cf9,0x3df7bd09,0x3db93db1,0x3c493dff,0xbd2cbdf1,0xbdc2bda7,0x3cafbdfc,0x3dc6bda2,0xbd983dce,0xbc7b3dfe,0xbdea3d4f,0xbdf5bd15,0x3e003bc9,0x3de5bd66,0x3dd83d89,
0xbdb53d80,0xbde7bd5b,0xbdfc3caf,0xbd7cbddf,0xbde23d71,0xbd983dce,0xbb493e00,0xbdf33d21,0x3d153df5,0x3dac3dbe,0x3dfa3ce0,0x3c7b3dfe,0x3dffbc49,0x3ddcbd84,0x3d4fbdea,0x3dff3c17,
0x3db53d80,0x3dce3d98,0x3dffbc17,0x3ce03dfa,0xbdc6bda2,0x3e003bc9,0x3dcabd9d,0x3db93db1,0xbdffbc49,0x3ddcbd84,0x3d21bdf3,0x3dfc3caf,0xbde23d71,0x3d5bbde7,0xbd09bdf7,0x3deabd4f,
0xbdb53d80,0xbdacbdbe,0xbe00bb49,0x3c17bdff,0x3d15bdf5,0xbd84bddc,0xbdfabce0,0x3d09bdf7,0x3d71bde2,0xbd2cbdf1,0xbdeabd4f,0x3d66bde5,0x3da2bdc6,0xbc96bdfd,0xbdd1bd93,0x3d9dbdca,
0x3db53d80,0x3d843ddc,0x3dfe3c7b,0xbd383def,0x3dffbc49,0xbd5b3de7,0x3d663de5,0xbdfa3ce0,0x3da23dc6,0xbdfd3c96,0xbd7c3ddf,0xbdb9bdb1,0xbd153df5,0xbdacbdbe,0xbdff3c17,0x3cafbdfc,
0xbdb53d80,0xbd2cbdf1,0xbdfabce0,0x3d9dbdca,0x3d713de2,0x3dfdbc96,0x3d4fbdea,0x3da73dc2,0xbdf53d15,0xbbc93e00,0x3dd13d93,0xbddf3d7c,0xbc49bdff,0xbdf8bcf9,0xbdb93db1,0xbd21bdf3,
0x3db53d80,0x3c963dfd,0x3df33d21,0xbdd13d93,0xbda23dc6,0xbdacbdbe,0xbdf73d09,0x3d38bdef,0x3c49bdff,0x3df83cf9,0x3da7bdc2,0x3ce03dfa,0x3d713de2,0xbdf13d2c,0xbc7b3dfe,0xbdb9bdb1,
0xbdb53d80,0x3bc9be00,0xbdeabd4f,0x3df3bd21,0xbdf5bd15,0xbcf93df8,0x3dd13d93,0xbdfe3c7b,0x3de23d71,0x3d5bbde7,0xbdb1bdb9,0x3dff3c17,0xbdc6bda2,0xbd983dce,0x3d893dd8,0xbdf7bd09,
0x3db53d80,0xbcf93df8,0x3ddf3d7c,0xbe003b49,0xbc49bdff,0x3df1bd2c,0xbc17bdff,0x3d933dd1,0xbdc63da2,0xbdcebd98,0xbdca3d9d,0x3d38bdef,0x3df53d15,0xbbc93e00,0x3df33d21,0xbdfa3ce0,
0xbdb53d80,0x3d5bbde7,0xbdd1bd93,0x3df73d09,0x3de2bd71,0xbdcebd98,0xbdb93db1,0x3d66bde5,0xbd15bdf5,0xbdbe3dac,0x3d893dd8,0xbdcabd9d,0xbdff3c49,0x3d843ddc,0x3defbd38,0xbdc23da7,
0x3db53d80,0xbd983dce,0x3dc23da7,0xbdd8bd89,0x3dc63da2,0xbbc93e00,0x3dfe3c7b,0xbe003b49,0x3dff3c49,0x3d843ddc,0x3de5bd66,0xbdd13d93,0x3de2bd71,0x3de73d5b,0x3d7cbddf,0xbd383def,
0xbdb53d80,0x3dbebdac,0xbdb1bdb9,0x3da73dc2,0xbd153df5,0x3ddcbd84,0xbd89bdd8,0x3d7c3ddf,0xbd713de2,0x3df1bd2c,0xbd38bdef,0x3d213df3,0xbda23dc6,0x3dfdbc96,0xbcafbdfc,0x3c7b3dfe,
0x3db53d80,0xbddc3d84,0x3d9d3dca,0xbd4fbdea,0xbdff3c49,0xbde7bd5b,0xbd213df3,0x3d89bdd8,0xbda2bdc6,0xbc96bdfd,0xbdf73d09,0x3e00bb49,0x3d15bdf5,0x3dbebdac,0xbdc2bda7,0x3d933dd1,
0xbdb53d80,0x3df1bd2c,0xbd89bdd8,0x3c7b3dfe,0xbd71bde2,0x3c963dfd,0x3defbd38,0xbdffbc17,0x3df5bd15,0xbe00bbc9,0x3caf3dfc,0x3d09bdf7,0x3c493dff,0x3cf9bdf8,0xbe00bb49,0x3de53d66,
0x3db53d80,0xbdfd3c96,0x3d663de5,0x3cafbdfc,0x3da2bdc6,0x3dbebdac,0xbddfbd7c,0x3d4f3dea,0xbc493dff,0xbcf93df8,0x3dffbc17,0xbdd8bd89,0xbd71bde2,0xbd2cbdf1,0xbdca3d9d,0x3e00bb49,
0xbdb53d80,0x3e003bc9,0xbd38bdef,0xbd663de5,0x3df53d15,0xbdf8bcf9,0x3caf3dfc,0x3d9dbdca,0xbde2bd71,0x3de73d5b,0x3b49be00,0xbdc23da7,0x3dc63da2,0xbdcebd98,0xbce03dfa,0x3ddfbd7c,
0x3db53d80,0xbdf8bcf9,0x3d093df7,0x3db1bdb9,0x3c493dff,0x3d2c3df1,0x3da7bdc2,0xbdfcbcaf,0x3dc6bda2,0x3d98bdce,0xbdfebc7b,0x3d4f3dea,0xbdf5bd15,0xbe00bbc9,0x3d663de5,0x3d89bdd8,
0xbdb53d80,0x3de73d5b,0xbcafbdfc,0xbddf3d7c,0xbde23d71,0x3d98bdce,0xbe00bb49,0x3d213df3,0x3d153df5,0xbdacbdbe,0xbce03dfa,0x3dfebc7b,0x3dffbc49,0xbddc3d84,0x3dea3d4f,0x3c17bdff,
0x3db53d80,0xbdcebd98,0x3c173dff,0x3dfabce0,0xbdc6bda2,0xbe00bbc9,0x3d9d3dca,0x3db1bdb9,0xbdffbc49,0xbddc3d84,0x3df33d21,0x3cafbdfc,0xbde23d71,0xbd5b3de7,0x3df7bd09,0xbd4fbdea,
0xbdb53d80,0x3dac3dbe,0x3b49be00,0xbdffbc17,0x3d15bdf5,0x3d843ddc,0x3ce0bdfa,0xbdf7bd09,0x3d71bde2,0x3d2c3df1,0x3d4fbdea,0xbde5bd66,0x3da2bdc6,0x3c963dfd,0x3d93bdd1,0xbdcabd9d,
0x3db53d80,0xbd84bddc,0xbc7b3dfe,0x3def3d38,0x3dffbc49,0x3d5bbde7,0xbde53d66,0x3ce03dfa,0x3da23dc6,0x3dfdbc96,0xbddfbd7c,0xbdb13db9,0xbd153df5,0x3dac3dbe,0xbc17bdff,0xbdfcbcaf,
0xbdb53d80,0x3d2c3df1,0x3ce0bdfa,0xbdcabd9d,0x3d713de2,0xbdfd3c96,0x3dea3d4f,0x3dc2bda7,0xbdf53d15,0x3bc9be00,0xbd933dd1,0x3d7c3ddf,0xbc49bdff,0x3df83cf9,0xbdb1bdb9,0xbdf33d21,
0x3db53d80,0xbc96bdfd,0xbd213df3,0x3d933dd1,0xbda23dc6,0x3dac3dbe,0xbd09bdf7,0xbdefbd38,0x3c49bdff,0xbdf8bcf9,0x3dc23da7,0x3dfabce0,0x3d713de2,0x3df1bd2c,0xbdfebc7b,0xbdb13db9,
0xbdb53d80,0xbbc93e00,0x3d4fbdea,0xbd21bdf3,0xbdf5bd15,0x3cf9bdf8,0xbd933dd1,0x3c7b3dfe,0x3de23d71,0xbd5b3de7,0x3db9bdb1,0x3c17bdff,0xbdc6bda2,0x3d98bdce,0xbdd83d89,0xbd093df7,
0x3db53d80,0x3cf9bdf8,0xbd7c3ddf,0x3b493e00,0xbc49bdff,0xbdf13d2c,0x3dffbc17,0x3dd1bd93,0xbdc63da2,0x3dce3d98,0xbd9dbdca,0xbdefbd38,0x3df53d15,0x3bc9be00,0xbd213df3,0x3ce03dfa,
0xbdb53d80,0xbd5b3de7,0x3d93bdd1,0x3d09bdf7,0x3de2bd71,0x3dce3d98,0xbdb1bdb9,0xbde5bd66,0xbd15bdf5,0x3dbebdac,0xbdd83d89,0xbd9d3dca,0xbdff3c49,0xbd84bddc,0x3d383def,0x3da73dc2,
0x3db53d80,0x3d98bdce,0xbda73dc2,0xbd893dd8,0x3dc63da2,0x3bc9be00,0xbc7b3dfe,0x3b493e00,0x3dff3c49,0xbd84bddc,0x3d663de5,0x3d933dd1,0x3de2bd71,0xbde7bd5b,0x3ddf3d7c,0x3def3d38,
0xbcc83dfb,0xbc493dff,0xbbc93e00,0xbc963dfd,0xbd443ded,0xbd713de2,0xbd5b3de7,0xbd843ddc,0xbdb53db5,0xbdc63da2,0xbdbe3dac,0xbdce3d98,0xbded3d44,0xbdf53d15,0xbdf13d2c,0xbdf83cf9,
0xbd8e3dd5,0xbd153df5,0xbc963dfd,0xbd5b3de7,0xbded3d44,0xbdff3c49,0xbdf83cf9,0xbe00bbc9,0xbdb5bdb5,0xbd71bde2,0xbd98bdce,0xbd2cbdf1,0x3d44bded,0x3da2bdc6,0x3d84bddc,0x3dbebdac,
0xbdd53d8e,0xbd713de2,0xbcf93df8,0xbdac3dbe,0xbdedbd44,0xbda2bdc6,0xbdcebd98,0xbd5bbde7,0x3db5bdb5,0x3df5bd15,0x3ddcbd84,0x3e00bbc9,0x3d443ded,0xbc493dff,0x3c963dfd,0xbd2c3df1,
0xbdfb3cc8,0xbda23dc6,0xbd2c3df1,0xbddc3d84,0xbd44bded,0x3d15bdf5,0xbbc9be00,0x3d98bdce,0x3db53db5,0x3c493dff,0x3d5b3de7,0xbcf93df8,0xbdedbd44,0xbd71bde2,0xbdbebdac,0xbc96bdfd,
0xbdfbbcc8,0xbdc63da2,0xbd5b3de7,0xbdf83cf9,0x3d44bded,0x3df5bd15,0x3dbebdac,0x3dfd3c96,0xbdb53db5,0xbdffbc49,0xbdf13d2c,0xbddcbd84,0x3dedbd44,0x3de23d71,0x3e003bc9,0x3d983dce,
0xbdd5bd8e,0xbde23d71,0xbd843ddc,0xbe00bbc9,0x3dedbd44,0x3dc63da2,0x3dfd3c96,0x3d2c3df1,0xbdb5bdb5,0x3d15bdf5,0xbcf9bdf8,0x3dbebdac,0xbd443ded,0xbdff3c49,0xbdce3d98,0xbde7bd5b,
0xbd8ebdd5,0xbdf53d15,0xbd983dce,0xbdf1bd2c,0x3ded3d44,0xbc493dff,0x3d843ddc,0xbdac3dbe,0x3db5bdb5,0x3de23d71,0x3dfdbc96,0x3d5b3de7,0xbd44bded,0x3dc6bda2,0x3cf9bdf8,0x3e00bbc9,
0xbcc8bdfb,0xbdff3c49,0xbdac3dbe,0xbdcebd98,0x3d443ded,0xbde23d71,0xbd2c3df1,0xbdf8bcf9,0x3db53db5,0xbda23dc6,0x3bc93e00,0xbdfd3c96,0x3ded3d44,0xbd153df5,0x3d5b3de7,0xbddc3d84,
0x3cc8bdfb,0xbdffbc49,0xbdbe3dac,0xbd98bdce,0xbd443ded,0xbde2bd71,0xbdf13d2c,0xbcf9bdf8,0xbdb53db5,0xbda2bdc6,0xbe00bbc9,0x3c96bdfd,0xbded3d44,0xbd15bdf5,0xbde7bd5b,0x3d84bddc,
0x3d8ebdd5,0xbdf5bd15,0xbdce3d98,0xbd2cbdf1,0xbded3d44,0xbc49bdff,0xbddcbd84,0x3dbebdac,0xbdb5bdb5,0x3de2bd71,0x3c96bdfd,0x3de73d5b,0x3d44bded,0x3dc63da2,0x3df8bcf9,0xbbc93e00,
0x3dd5bd8e,0xbde2bd71,0xbddc3d84,0xbbc9be00,0xbdedbd44,0x3dc6bda2,0xbc96bdfd,0x3df13d2c,0x3db5bdb5,0x3d153df5,0x3df83cf9,0xbdac3dbe,0x3d443ded,0xbdffbc49,0xbd983dce,0xbd5bbde7,
0x3dfbbcc8,0xbdc6bda2,0xbde73d5b,0x3cf9bdf8,0xbd44bded,0x3df53d15,0x3dacbdbe,0x3c963dfd,0x3db53db5,0xbdff3c49,0xbd2c3df1,0xbd84bddc,0xbdedbd44,0x3de2bd71,0xbbc9be00,0x3dce3d98,
0x3dfb3cc8,0xbda2bdc6,0xbdf13d2c,0x3d84bddc,0x3d44bded,0x3d153df5,0x3e003bc9,0xbdce3d98,0xbdb53db5,0x3c49bdff,0xbde7bd5b,0x3df8bcf9,0x3dedbd44,0xbd713de2,0x3dac3dbe,0xbdfdbc96,
0x3dd53d8e,0xbd71bde2,0xbdf83cf9,0x3dbebdac,0x3dedbd44,0xbda23dc6,0x3d983dce,0xbde7bd5b,0xbdb5bdb5,0x3df53d15,0x3d84bddc,0xbbc93e00,0xbd443ded,0xbc49bdff,0xbdfdbc96,0x3df1bd2c,
0x3d8e3dd5,0xbd15bdf5,0xbdfd3c96,0x3de7bd5b,0x3ded3d44,0xbdffbc49,0xbcf93df8,0xbbc9be00,0x3db5bdb5,0xbd713de2,0x3dce3d98,0xbdf1bd2c,0xbd44bded,0x3da23dc6,0x3ddcbd84,0xbdac3dbe,
0x3cc83dfb,0xbc49bdff,0xbe003bc9,0x3dfdbc96,0x3d443ded,0xbd71bde2,0xbde73d5b,0x3ddcbd84,0x3db53db5,0xbdc6bda2,0xbdac3dbe,0x3d98bdce,0x3ded3d44,0xbdf5bd15,0xbd2c3df1,0x3cf9bdf8,
0xbcc83dfb,0x3c49bdff,0xbe00bbc9,0x3dfd3c96,0xbd443ded,0x3d71bde2,0xbde7bd5b,0x3ddc3d84,0xbdb53db5,0x3dc6bda2,0xbdacbdbe,0x3d983dce,0xbded3d44,0x3df5bd15,0xbd2cbdf1,0x3cf93df8,
0xbd8e3dd5,0x3d15bdf5,0xbdfdbc96,0x3de73d5b,0xbded3d44,0x3dffbc49,0xbcf9bdf8,0xbbc93e00,0xbdb5bdb5,0x3d713de2,0x3dcebd98,0xbdf13d2c,0x3d44bded,0xbda23dc6,0x3ddc3d84,0xbdacbdbe,
0xbdd53d8e,0x3d71bde2,0xbdf8bcf9,0x3dbe3dac,0xbdedbd44,0x3da23dc6,0x3d98bdce,0xbde73d5b,0x3db5bdb5,0xbdf53d15,0x3d843ddc,0xbbc9be00,0x3d443ded,0x3c49bdff,0xbdfd3c96,0x3df13d2c,
0xbdfb3cc8,0x3da2bdc6,0xbdf1bd2c,0x3d843ddc,0xbd44bded,0xbd153df5,0x3e00bbc9,0xbdcebd98,0x3db53db5,0xbc49bdff,0xbde73d5b,0x3df83cf9,0xbdedbd44,0x3d713de2,0x3dacbdbe,0xbdfd3c96,
0xbdfbbcc8,0x3dc6bda2,0xbde7bd5b,0x3cf93df8,0x3d44bded,0xbdf53d15,0x3dac3dbe,0x3c96bdfd,0xbdb53db5,0x3dff3c49,0xbd2cbdf1,0xbd843ddc,0x3dedbd44,0xbde2bd71,0xbbc93e00,0x3dcebd98,
0xbdd5bd8e,0x3de2bd71,0xbddcbd84,0xbbc93e00,0x3dedbd44,0xbdc6bda2,0xbc963dfd,0x3df1bd2c,0xbdb5bdb5,0xbd153df5,0x3df8bcf9,0xbdacbdbe,0xbd443ded,0x3dffbc49,0xbd98bdce,0xbd5b3de7,
0xbd8ebdd5,0x3df5bd15,0xbdcebd98,0xbd2c3df1,0x3ded3d44,0x3c49bdff,0xbddc3d84,0x3dbe3dac,0x3db5bdb5,0xbde2bd71,0x3c963dfd,0x3de7bd5b,0xbd44bded,0xbdc63da2,0x3df83cf9,0xbbc9be00,
0xbcc8bdfb,0x3dffbc49,0xbdbebdac,0xbd983dce,0x3d443ded,0x3de2bd71,0xbdf1bd2c,0xbcf93df8,0x3db53db5,0x3da2bdc6,0xbe003bc9,0x3c963dfd,0x3ded3d44,0x3d15bdf5,0xbde73d5b,0x3d843ddc,
0x3cc8bdfb,0x3dff3c49,0xbdacbdbe,0xbdce3d98,0xbd443ded,0x3de23d71,0xbd2cbdf1,0xbdf83cf9,0xbdb53db5,0x3da23dc6,0x3bc9be00,0xbdfdbc96,0xbded3d44,0x3d153df5,0x3d5bbde7,0xbddcbd84,
0x3d8ebdd5,0x3df53d15,0xbd98bdce,0xbdf13d2c,0xbded3d44,0x3c493dff,0x3d84bddc,0xbdacbdbe,0xbdb5bdb5,0xbde23d71,0x3dfd3c96,0x3d5bbde7,0x3d44bded,0xbdc6bda2,0x3cf93df8,0x3e003bc9,
0x3dd5bd8e,0x3de23d71,0xbd84bddc,0xbe003bc9,0xbdedbd44,0xbdc63da2,0x3dfdbc96,0x3d2cbdf1,0x3db5bdb5,0xbd15bdf5,0xbcf93df8,0x3dbe3dac,0x3d443ded,0x3dff3c49,0xbdcebd98,0xbde73d5b,
0x3dfbbcc8,0x3dc63da2,0xbd5bbde7,0xbdf8bcf9,0xbd44bded,0xbdf5bd15,0x3dbe3dac,0x3dfdbc96,0x3db53db5,0x3dffbc49,0xbdf1bd2c,0xbddc3d84,0xbdedbd44,0xbde23d71,0x3e00bbc9,0x3d98bdce,
0x3dfb3cc8,0x3da23dc6,0xbd2cbdf1,0xbddcbd84,0x3d44bded,0xbd15bdf5,0xbbc93e00,0x3d983dce,0xbdb53db5,0xbc493dff,0x3d5bbde7,0xbcf9bdf8,0x3dedbd44,0x3d71bde2,0xbdbe3dac,0xbc963dfd,
0x3dd53d8e,0x3d713de2,0xbcf9bdf8,0xbdacbdbe,0x3dedbd44,0x3da2bdc6,0xbdce3d98,0xbd5b3de7,0xbdb5bdb5,0xbdf5bd15,0x3ddc3d84,0x3e003bc9,0xbd443ded,0x3c493dff,0x3c96bdfd,0xbd2cbdf1,
0x3d8e3dd5,0x3d153df5,0xbc96bdfd,0xbd5bbde7,0x3ded3d44,0x3dff3c49,0xbdf8bcf9,0xbe003bc9,0x3db5bdb5,0x3d71bde2,0xbd983dce,0xbd2c3df1,0xbd44bded,0xbda2bdc6,0x3d843ddc,0x3dbe3dac,
0x3cc83dfb,0x3c493dff,0xbbc9be00,0xbc96bdfd,0x3d443ded,0x3d713de2,0xbd5bbde7,0xbd84bddc,0x3db53db5,0x3dc63da2,0xbdbebdac,0xbdcebd98,0x3ded3d44,0x3df53d15,0xbdf1bd2c,0xbdf8bcf9,
0xbd803d80,0xbdffbc49,0xbe00bbc9,0xbdfdbc96,0xbd8e3dd5,0xbde2bd71,0xbde7bd5b,0xbddcbd84,0xbdd53d8e,0xbda2bdc6,0xbdacbdbe,0xbd98bdce,0xbdfb3cc8,0xbd15bdf5,0xbd2cbdf1,0xbcf9bdf8,
0x3d803d80,0x3df53d15,0x3dfd3c96,0x3de73d5b,0xbdfbbcc8,0x3c493dff,0x3cf93df8,0xbbc93e00,0xbcc8bdfb,0xbde23d71,0xbdce3d98,0xbdf13d2c,0x3dd5bd8e,0xbdc6bda2,0xbddcbd84,0xbdacbdbe,
0xbd803d80,0xbde2bd71,0xbdf8bcf9,0xbdbebdac,0xbcc8bdfb,0x3dc6bda2,0x3d98bdce,0x3de7bd5b,0x3dfb3cc8,0x3d153df5,0x3d843ddc,0x3bc93e00,0xbd8e3dd5,0xbdffbc49,0xbdfd3c96,0xbdf1bd2c,
0x3d803d80,0x3dc63da2,0x3df13d2c,0x3d843ddc,0x3dd5bd8e,0xbdf5bd15,0xbe003bc9,0xbdcebd98,0xbd8e3dd5,0x3dffbc49,0x3de7bd5b,0x3df83cf9,0x3cc8bdfb,0xbde23d71,0xbdac3dbe,0xbdfd3c96,
0xbd803d80,0xbda2bdc6,0xbde7bd5b,0xbcf9bdf8,0x3dd53d8e,0x3d153df5,0x3dac3dbe,0xbc963dfd,0xbd8ebdd5,0x3c49bdff,0xbd2cbdf1,0x3d84bddc,0x3cc83dfb,0xbd713de2,0xbbc93e00,0xbdce3d98,
0x3d803d80,0x3d713de2,0x3ddc3d84,0xbbc93e00,0xbcc83dfb,0x3da2bdc6,0x3c96bdfd,0x3df1bd2c,0x3dfbbcc8,0xbdf5bd15,0xbdf83cf9,0xbdacbdbe,0xbd8ebdd5,0x3c493dff,0x3d983dce,0xbd5b3de7,
0xbd803d80,0xbd15bdf5,0xbdcebd98,0x3d2cbdf1,0xbdfb3cc8,0xbdffbc49,0xbddc3d84,0xbdbebdac,0xbcc83dfb,0xbd713de2,0x3c963dfd,0xbde73d5b,0x3dd53d8e,0x3da23dc6,0x3df83cf9,0x3bc93e00,
0x3d803d80,0x3c493dff,0x3dbe3dac,0xbd983dce,0xbd8ebdd5,0x3d713de2,0x3df13d2c,0xbcf93df8,0xbdd5bd8e,0x3dc63da2,0x3e00bbc9,0x3c963dfd,0xbdfbbcc8,0x3df53d15,0x3de7bd5b,0x3d843ddc,
0xbd803d80,0x3c49bdff,0xbdacbdbe,0x3dcebd98,0x3d8ebdd5,0x3d71bde2,0xbd2cbdf1,0x3df8bcf9,0x3dd5bd8e,0x3dc6bda2,0x3bc9be00,0x3dfd3c96,0x3dfbbcc8,0x3df5bd15,0x3d5bbde7,0x3ddc3d84,
0x3d803d80,0xbd153df5,0x3d983dce,0xbdf13d2c,0x3dfb3cc8,0xbdff3c49,0xbd843ddc,0xbdacbdbe,0x3cc83dfb,0xbd71bde2,0xbdfdbc96,0x3d5bbde7,0xbdd53d8e,0x3da2bdc6,0xbcf9bdf8,0x3e003bc9,
0xbd803d80,0x3d71bde2,0xbd84bddc,0x3e00bbc9,0x3cc83dfb,0x3da23dc6,0x3dfdbc96,0xbd2c3df1,0xbdfbbcc8,0xbdf53d15,0xbcf93df8,0xbdbebdac,0x3d8ebdd5,0x3c49bdff,0xbdcebd98,0x3de7bd5b,
0x3d803d80,0xbda23dc6,0x3d5b3de7,0xbdf8bcf9,0xbdd53d8e,0x3d15bdf5,0xbdbebdac,0x3dfdbc96,0x3d8ebdd5,0x3c493dff,0x3df13d2c,0xbddc3d84,0xbcc83dfb,0xbd71bde2,0xbe003bc9,0x3d98bdce,
0xbd803d80,0x3dc6bda2,0xbd2cbdf1,0x3ddc3d84,0xbdd5bd8e,0xbdf53d15,0xbbc93e00,0xbd98bdce,0x3d8e3dd5,0x3dff3c49,0x3d5bbde7,0x3cf93df8,0xbcc8bdfb,0xbde2bd71,0xbdbe3dac,0x3c96bdfd,
0x3d803d80,0xbde23d71,0x3cf93df8,0xbdacbdbe,0x3cc8bdfb,0x3dc63da2,0x3dcebd98,0xbd5b3de7,0xbdfb3cc8,0x3d15bdf5,0xbddcbd84,0x3e003bc9,0x3d8e3dd5,0xbdff3c49,0xbc963dfd,0xbd2cbdf1,
0xbd803d80,0x3df5bd15,0xbc96bdfd,0x3d5b3de7,0x3dfbbcc8,0x3c49bdff,0xbdf8bcf9,0x3e00bbc9,0x3cc8bdfb,0xbde2bd71,0xbd983dce,0x3d2cbdf1,0xbdd5bd8e,0xbdc63da2,0x3d843ddc,0xbdbebdac,
0x3d803d80,0xbdff3c49,0x3bc93e00,0xbc96bdfd,0x3d8e3dd5,0xbde23d71,0x3d5b3de7,0xbd84bddc,0x3dd53d8e,0xbda23dc6,0x3dbe3dac,0xbdcebd98,0x3dfb3cc8,0xbd153df5,0x3df13d2c,0xbdf8bcf9,
0xbd803d80,0x3dff3c49,0x3bc9be00,0xbc963dfd,0xbd8e3dd5,0x3de23d71,0x3d5bbde7,0xbd843ddc,0xbdd53d8e,0x3da23dc6,0x3dbebdac,0xbdce3d98,0xbdfb3cc8,0x3d153df5,0x3df1bd2c,0xbdf83cf9,
0x3d803d80,0xbdf5bd15,0xbc963dfd,0x3d5bbde7,0xbdfbbcc8,0xbc49bdff,0xbdf83cf9,0x3e003bc9,0xbcc8bdfb,0x3de2bd71,0xbd98bdce,0x3d2c3df1,0x3dd5bd8e,0x3dc63da2,0x3d84bddc,0xbdbe3dac,
0xbd803d80,0x3de23d71,0x3cf9bdf8,0xbdac3dbe,0xbcc8bdfb,0xbdc63da2,0x3dce3d98,0xbd5bbde7,0x3dfb3cc8,0xbd15bdf5,0xbddc3d84,0x3e00bbc9,0xbd8e3dd5,0x3dff3c49,0xbc96bdfd,0xbd2c3df1,
0x3d803d80,0xbdc6bda2,0xbd2c3df1,0x3ddcbd84,0x3dd5bd8e,0x3df53d15,0xbbc9be00,0xbd983dce,0xbd8e3dd5,0xbdff3c49,0x3d5b3de7,0x3cf9bdf8,0x3cc8bdfb,0x3de2bd71,0xbdbebdac,0x3c963dfd,
0xbd803d80,0x3da23dc6,0x3d5bbde7,0xbdf83cf9,0x3dd53d8e,0xbd15bdf5,0xbdbe3dac,0x3dfd3c96,0xbd8ebdd5,0xbc493dff,0x3df1bd2c,0xbddcbd84,0x3cc83dfb,0x3d71bde2,0xbe00bbc9,0x3d983dce,
0x3d803d80,0xbd71bde2,0xbd843ddc,0x3e003bc9,0xbcc83dfb,0xbda23dc6,0x3dfd3c96,0xbd2cbdf1,0x3dfbbcc8,0x3df53d15,0xbcf9bdf8,0xbdbe3dac,0xbd8ebdd5,0xbc49bdff,0xbdce3d98,0x3de73d5b,
0xbd803d80,0x3d153df5,0x3d98bdce,0xbdf1bd2c,0xbdfb3cc8,0x3dff3c49,0xbd84bddc,0xbdac3dbe,0xbcc83dfb,0x3d71bde2,0xbdfd3c96,0x3d5b3de7,0x3dd53d8e,0xbda2bdc6,0xbcf93df8,0x3e00bbc9,
0x3d803d80,0xbc49bdff,0xbdac3dbe,0x3dce3d98,0xbd8ebdd5,0xbd71bde2,0xbd2c3df1,0x3df83cf9,0xbdd5bd8e,0xbdc6bda2,0x3bc93e00,0x3dfdbc96,0xbdfbbcc8,0xbdf5bd15,0x3d5b3de7,0x3ddcbd84,
0xbd803d80,0xbc493dff,0x3dbebdac,0xbd98bdce,0x3d8ebdd5,0xbd713de2,0x3df1bd2c,0xbcf9bdf8,0x3dd5bd8e,0xbdc63da2,0x3e003bc9,0x3c96bdfd,0x3dfbbcc8,0xbdf53d15,0x3de73d5b,0x3d84bddc,
0x3d803d80,0x3d15bdf5,0xbdce3d98,0x3d2c3df1,0x3dfb3cc8,0x3dffbc49,0xbddcbd84,0xbdbe3dac,0x3cc83dfb,0x3d713de2,0x3c96bdfd,0xbde7bd5b,0xbdd53d8e,0xbda23dc6,0x3df8bcf9,0x3bc9be00,
0xbd803d80,0xbd713de2,0x3ddcbd84,0xbbc9be00,0x3cc83dfb,0xbda2bdc6,0x3c963dfd,0x3df13d2c,0xbdfbbcc8,0x3df5bd15,0xbdf8bcf9,0xbdac3dbe,0x3d8ebdd5,0xbc493dff,0x3d98bdce,0xbd5bbde7,
0x3d803d80,0x3da2bdc6,0xbde73d5b,0xbcf93df8,0xbdd53d8e,0xbd153df5,0x3dacbdbe,0xbc96bdfd,0x3d8ebdd5,0xbc49bdff,0xbd2c3df1,0x3d843ddc,0xbcc83dfb,0x3d713de2,0xbbc9be00,0xbdcebd98,
0xbd803d80,0xbdc63da2,0x3df1bd2c,0x3d84bddc,0xbdd5bd8e,0x3df5bd15,0xbe00bbc9,0xbdce3d98,0x3d8e3dd5,0xbdffbc49,0x3de73d5b,0x3df8bcf9,0xbcc8bdfb,0x3de23d71,0xbdacbdbe,0xbdfdbc96,
0x3d803d80,0x3de2bd71,0xbdf83cf9,0xbdbe3dac,0x3cc8bdfb,0xbdc6bda2,0x3d983dce,0x3de73d5b,0xbdfb3cc8,0xbd153df5,0x3d84bddc,0x3bc9be00,0x3d8e3dd5,0x3dffbc49,0xbdfdbc96,0xbdf13d2c,
0xbd803d80,0xbdf53d15,0x3dfdbc96,0x3de7bd5b,0x3dfbbcc8,0xbc493dff,0x3cf9bdf8,0xbbc9be00,0x3cc8bdfb,0x3de23d71,0xbdcebd98,0xbdf1bd2c,0xbdd5bd8e,0x3dc6bda2,0xbddc3d84,0xbdac3dbe,
0x3d803d80,0x3dffbc49,0xbe003bc9,0xbdfd3c96,0x3d8e3dd5,0x3de2bd71,0xbde73d5b,0xbddc3d84,0x3dd53d8e,0x3da2bdc6,0xbdac3dbe,0xbd983dce,0x3dfb3cc8,0x3d15bdf5,0xbd2c3df1,0xbcf93df8,
0xbd153df5,0xbc963dfd,0xbc173dff,0xbce03dfa,0xbd8e3dd5,0xbdac3dbe,0xbd9d3dca,0xbdb93db1,0xbded3d44,0xbdf83cf9,0xbdf33d21,0xbdfc3caf,0xbdfbbcc8,0xbdf1bd2c,0xbdf7bd09,0xbdeabd4f,
0xbda23dc6,0xbd2c3df1,0xbcaf3dfc,0xbd7c3ddf,0xbdfb3cc8,0xbdfdbc96,0xbe003b49,0xbdf3bd21,0xbd44bded,0xbbc9be00,0xbce0bdfa,0x3c7bbdfe,0x3dd5bd8e,0x3df8bcf9,0x3deabd4f,0x3dffbc17,
0xbde23d71,0xbd843ddc,0xbd093df7,0xbdb93db1,0xbdd5bd8e,0xbd5bbde7,0xbda7bdc2,0xbcafbdfc,0x3dedbd44,0x3dfd3c96,0x3dfebc7b,0x3dea3d4f,0xbcc83dfb,0xbdac3dbe,0xbd663de5,0xbdd83d89,
0xbdff3c49,0xbdac3dbe,0xbd383def,0xbde53d66,0xbcc8bdfb,0x3d84bddc,0x3cafbdfc,0x3dcabd9d,0x3d443ded,0xbd2c3df1,0x3b493e00,0xbda73dc2,0xbd8ebdd5,0x3c96bdfd,0xbce0bdfa,0x3d7cbddf,
0xbdf5bd15,0xbdce3d98,0xbd663de5,0xbdfc3caf,0x3d8ebdd5,0x3e00bbc9,0x3ddfbd7c,0x3dea3d4f,0xbded3d44,0xbddcbd84,0xbdffbc17,0xbd89bdd8,0x3dfb3cc8,0x3d5b3de7,0x3dca3d9d,0xbb493e00,
0xbdc6bda2,0xbde73d5b,0xbd893dd8,0xbdfebc7b,0x3dfbbcc8,0x3d983dce,0x3def3d38,0x3c173dff,0xbd44bded,0x3dacbdbe,0x3cafbdfc,0x3df7bd09,0xbdd53d8e,0xbddcbd84,0xbe003b49,0xbd66bde5,
0xbd71bde2,0xbdf83cf9,0xbd9d3dca,0xbdeabd4f,0x3dd53d8e,0xbd2c3df1,0x3d213df3,0xbdd83d89,0x3dedbd44,0x3d983dce,0x3df73d09,0xbb493e00,0x3cc8bdfb,0x3e00bbc9,0x3dc2bda7,0x3dd13d93,
0xbc49bdff,0xbe003bc9,0xbdb13db9,0xbdc2bda7,0x3cc83dfb,0xbdf83cf9,0xbd893dd8,0xbddfbd7c,0x3d443ded,0xbde73d5b,0xbd383def,0xbdf3bd21,0x3d8e3dd5,0xbdce3d98,0xbcaf3dfc,0xbdfebc7b,
0x3d15bdf5,0xbdfdbc96,0xbdc23da7,0xbd89bdd8,0xbd8e3dd5,0xbdbebdac,0xbdfe3c7b,0x3b49be00,0xbded3d44,0xbcf9bdf8,0xbde5bd66,0x3d93bdd1,0xbdfbbcc8,0x3d2cbdf1,0xbd7cbddf,0x3defbd38,
0x3da2bdc6,0xbdf1bd2c,0xbdd13d93,0xbd09bdf7,0xbdfb3cc8,0x3c96bdfd,0xbdb9bdb1,0x3de5bd66,0xbd44bded,0x3e00bbc9,0x3d89bdd8,0x3d9d3dca,0x3dd5bd8e,0x3cf93df8,0x3def3d38,0xbda73dc2,
0x3de2bd71,0xbddcbd84,0xbddf3d7c,0x3b49be00,0xbdd5bd8e,0x3de7bd5b,0x3c17bdff,0x3dd13d93,0x3dedbd44,0xbc963dfd,0x3dca3d9d,0xbdef3d38,0xbcc83dfb,0xbdbebdac,0xbdf33d21,0x3ce0bdfa,
0x3dffbc49,0xbdbebdac,0xbdea3d4f,0x3d21bdf3,0xbcc8bdfb,0x3ddc3d84,0x3dd1bd93,0xbc7b3dfe,0x3d443ded,0xbdf1bd2c,0xbdb13db9,0xbc17bdff,0xbd8ebdd5,0x3dfd3c96,0x3d89bdd8,0x3d093df7,
0x3df53d15,0xbd98bdce,0xbdf33d21,0x3d93bdd1,0x3d8ebdd5,0x3bc93e00,0x3df73d09,0xbdef3d38,0xbded3d44,0x3d84bddc,0xbda7bdc2,0x3dfa3ce0,0x3dfb3cc8,0xbde73d5b,0x3c7b3dfe,0xbdb1bdb9,
0x3dc63da2,0xbd5bbde7,0xbdfa3ce0,0x3dcabd9d,0x3dfbbcc8,0xbdce3d98,0x3d4f3dea,0xbdc2bda7,0xbd44bded,0x3dbe3dac,0x3dd1bd93,0xbd7c3ddf,0xbdd53d8e,0x3d84bddc,0xbdb9bdb1,0x3df33d21,
0x3d713de2,0xbcf9bdf8,0xbdfe3c7b,0x3defbd38,0x3dd53d8e,0xbdf1bd2c,0xbd663de5,0x3ce0bdfa,0x3dedbd44,0xbdce3d98,0x3d7c3ddf,0xbdb1bdb9,0x3cc8bdfb,0x3bc93e00,0x3dff3c17,0xbdfc3caf,
0x3c493dff,0xbbc9be00,0xbe003b49,0x3dffbc17,0x3cc83dfb,0xbcf9bdf8,0xbdfa3ce0,0x3df7bd09,0x3d443ded,0xbd5bbde7,0xbdea3d4f,0x3de5bd66,0x3d8e3dd5,0xbd98bdce,0xbdd13d93,0x3dcabd9d,
0xbd153df5,0x3c96bdfd,0xbdffbc17,0x3dfa3ce0,0xbd8e3dd5,0x3dacbdbe,0xbdcabd9d,0x3db13db9,0xbded3d44,0x3df8bcf9,0xbd21bdf3,0x3caf3dfc,0xbdfbbcc8,0x3df13d2c,0x3d09bdf7,0xbd4f3dea,
0xbda23dc6,0x3d2cbdf1,0xbdfcbcaf,0x3ddf3d7c,0xbdfb3cc8,0x3dfd3c96,0xbb49be00,0xbd213df3,0xbd44bded,0x3bc93e00,0x3dfabce0,0xbdfebc7b,0x3dd5bd8e,0xbdf83cf9,0x3d4f3dea,0xbc17bdff,
0xbde23d71,0x3d84bddc,0xbdf7bd09,0x3db13db9,0xbdd5bd8e,0x3d5b3de7,0x3dc2bda7,0xbdfc3caf,0x3dedbd44,0xbdfdbc96,0x3c7b3dfe,0x3d4fbdea,0xbcc83dfb,0x3dacbdbe,0xbde5bd66,0x3d893dd8,
0xbdff3c49,0x3dacbdbe,0xbdefbd38,0x3d663de5,0xbcc8bdfb,0xbd843ddc,0x3dfc3caf,0xbd9dbdca,0x3d443ded,0x3d2cbdf1,0xbe003b49,0x3dc23da7,0xbd8ebdd5,0xbc963dfd,0x3dfabce0,0xbddfbd7c,
0xbdf5bd15,0x3dcebd98,0xbde5bd66,0x3caf3dfc,0x3d8ebdd5,0xbe003bc9,0x3d7c3ddf,0x3d4fbdea,0xbded3d44,0x3ddc3d84,0x3c17bdff,0xbdd83d89,0x3dfb3cc8,0xbd5bbde7,0xbd9d3dca,0x3e003b49,
0xbdc6bda2,0x3de7bd5b,0xbdd8bd89,0xbc7b3dfe,0x3dfbbcc8,0xbd98bdce,0xbd383def,0x3dffbc17,0xbd44bded,0xbdac3dbe,0x3dfc3caf,0xbd09bdf7,0xbdd53d8e,0x3ddc3d84,0xbb49be00,0xbde53d66,
0xbd71bde2,0x3df8bcf9,0xbdcabd9d,0xbd4f3dea,0x3dd53d8e,0x3d2cbdf1,0xbdf33d21,0x3d893dd8,0x3dedbd44,0xbd98bdce,0xbd093df7,0x3e003b49,0x3cc8bdfb,0xbe003bc9,0x3da73dc2,0x3d93bdd1,
0xbc49bdff,0x3e00bbc9,0xbdb9bdb1,0xbda73dc2,0x3cc83dfb,0x3df8bcf9,0xbdd8bd89,0xbd7c3ddf,0x3d443ded,0x3de7bd5b,0xbdefbd38,0xbd213df3,0x3d8e3dd5,0x3dcebd98,0xbdfcbcaf,0xbc7b3dfe,
0x3d15bdf5,0x3dfd3c96,0xbda7bdc2,0xbdd83d89,0xbd8e3dd5,0x3dbe3dac,0xbc7bbdfe,0xbe00bb49,0xbded3d44,0x3cf93df8,0x3d66bde5,0xbdd1bd93,0xbdfbbcc8,0xbd2c3df1,0x3ddfbd7c,0xbd38bdef,
0x3da2bdc6,0x3df13d2c,0xbd93bdd1,0xbdf73d09,0xbdfb3cc8,0xbc963dfd,0x3db1bdb9,0xbd66bde5,0xbd44bded,0xbe003bc9,0x3dd83d89,0x3dcabd9d,0x3dd5bd8e,0xbcf9bdf8,0xbd383def,0x3dc23da7,
0x3de2bd71,0x3ddc3d84,0xbd7cbddf,0xbe00bb49,0xbdd5bd8e,0xbde73d5b,0x3dff3c17,0x3d93bdd1,0x3dedbd44,0x3c96bdfd,0xbd9d3dca,0x3d383def,0xbcc83dfb,0x3dbe3dac,0xbd21bdf3,0xbdfabce0,
0x3dffbc49,0x3dbe3dac,0xbd4fbdea,0xbdf3bd21,0xbcc8bdfb,0xbddcbd84,0x3d933dd1,0x3dfe3c7b,0x3d443ded,0x3df13d2c,0xbdb9bdb1,0xbdff3c17,0xbd8ebdd5,0xbdfdbc96,0x3dd83d89,0x3df7bd09,
0x3df53d15,0x3d983dce,0xbd21bdf3,0xbdd1bd93,0x3d8ebdd5,0xbbc9be00,0xbd093df7,0x3d383def,0xbded3d44,0xbd843ddc,0x3dc2bda7,0x3ce0bdfa,0x3dfb3cc8,0x3de7bd5b,0xbdfe3c7b,0xbdb93db1,
0x3dc63da2,0x3d5b3de7,0xbce0bdfa,0xbd9dbdca,0x3dfbbcc8,0x3dcebd98,0xbdea3d4f,0xbda73dc2,0xbd44bded,0xbdbebdac,0x3d933dd1,0x3ddf3d7c,0xbdd53d8e,0xbd843ddc,0x3db1bdb9,0x3d21bdf3,
0x3d713de2,0x3cf93df8,0xbc7bbdfe,0xbd38bdef,0x3dd53d8e,0x3df13d2c,0xbde5bd66,0xbdfabce0,0x3dedbd44,0x3dcebd98,0xbddf3d7c,0xbdb93db1,0x3cc8bdfb,0xbbc9be00,0xbc173dff,0x3caf3dfc,
0x3c493dff,0x3bc93e00,0xbb49be00,0xbc17bdff,0x3cc83dfb,0x3cf93df8,0xbce0bdfa,0xbd09bdf7,0x3d443ded,0x3d5b3de7,0xbd4fbdea,0xbd66bde5,0x3d8e3dd5,0x3d983dce,0xbd93bdd1,0xbd9dbdca,
0xbdb53d80,0xbd98bdce,0xbda7bdc2,0xbd89bdd8,0xbdc63da2,0xbbc9be00,0xbc7bbdfe,0x3b49be00,0xbdff3c49,0x3d84bddc,0x3d66bde5,0x3d93bdd1,0xbde2bd71,0x3de7bd5b,0x3ddfbd7c,0x3defbd38,
0x3db53d80,0x3d5b3de7,0x3d933dd1,0x3d093df7,0xbde2bd71,0xbdce3d98,0xbdb13db9,0xbde53d66,0x3d15bdf5,0xbdbebdac,0xbdd8bd89,0xbd9dbdca,0x3dff3c49,0x3d84bddc,0x3d38bdef,0x3da7bdc2,
0xbdb53d80,0xbcf9bdf8,0xbd7cbddf,0x3b49be00,0x3c49bdff,0x3df13d2c,0x3dff3c17,0x3dd13d93,0x3dc63da2,0xbdce3d98,0xbd9d3dca,0xbdef3d38,0xbdf53d15,0xbbc9be00,0xbd21bdf3,0x3ce0bdfa,
0x3db53d80,0x3bc93e00,0x3d4f3dea,0xbd213df3,0x3df5bd15,0xbcf9bdf8,0xbd93bdd1,0x3c7bbdfe,0xbde23d71,0x3d5b3de7,0x3db93db1,0x3c173dff,0x3dc6bda2,0xbd98bdce,0xbdd8bd89,0xbd09bdf7,
0xbdb53d80,0x3c96bdfd,0xbd21bdf3,0x3d93bdd1,0x3da23dc6,0xbdac3dbe,0xbd093df7,0xbdef3d38,0xbc49bdff,0x3df8bcf9,0x3dc2bda7,0x3dfa3ce0,0xbd713de2,0xbdf1bd2c,0xbdfe3c7b,0xbdb1bdb9,
0x3db53d80,0xbd2c3df1,0x3ce03dfa,0xbdca3d9d,0xbd713de2,0x3dfd3c96,0x3deabd4f,0x3dc23da7,0x3df53d15,0xbbc9be00,0xbd93bdd1,0x3d7cbddf,0x3c49bdff,0xbdf83cf9,0xbdb13db9,0xbdf3bd21,
0xbdb53d80,0x3d84bddc,0xbc7bbdfe,0x3defbd38,0xbdffbc49,0xbd5bbde7,0xbde5bd66,0x3ce0bdfa,0xbda23dc6,0xbdfdbc96,0xbddf3d7c,0xbdb1bdb9,0x3d153df5,0xbdac3dbe,0xbc173dff,0xbdfc3caf,
0x3db53d80,0xbdac3dbe,0x3b493e00,0xbdff3c17,0xbd15bdf5,0xbd843ddc,0x3ce03dfa,0xbdf73d09,0xbd71bde2,0xbd2c3df1,0x3d4f3dea,0xbde53d66,0xbda2bdc6,0xbc963dfd,0x3d933dd1,0xbdca3d9d,
0xbdb53d80,0x3dcebd98,0x3c17bdff,0x3dfa3ce0,0x3dc6bda2,0x3e00bbc9,0x3d9dbdca,0x3db13db9,0x3dffbc49,0x3ddc3d84,0x3df3bd21,0x3caf3dfc,0x3de23d71,0x3d5b3de7,0x3df73d09,0xbd4f3dea,
0x3db53d80,0xbde73d5b,0xbcaf3dfc,0xbddfbd7c,0x3de23d71,0xbd98bdce,0xbe003b49,0x3d21bdf3,0xbd153df5,0x3dacbdbe,0xbce0bdfa,0x3dfe3c7b,0xbdffbc49,0x3ddc3d84,0x3deabd4f,0x3c173dff,
0xbdb53d80,0x3df8bcf9,0x3d09bdf7,0x3db13db9,0xbc493dff,0xbd2c3df1,0x3da73dc2,0xbdfc3caf,0xbdc6bda2,0xbd98bdce,0xbdfe3c7b,0x3d4fbdea,0x3df5bd15,0x3e00bbc9,0x3d66bde5,0x3d893dd8,
0x3db53d80,0xbe003bc9,0xbd383def,0xbd66bde5,0xbdf53d15,0x3df8bcf9,0x3cafbdfc,0x3d9d3dca,0x3de2bd71,0xbde73d5b,0x3b493e00,0xbdc2bda7,0xbdc63da2,0x3dcebd98,0xbce0bdfa,0x3ddf3d7c,
0xbdb53d80,0x3dfd3c96,0x3d66bde5,0x3caf3dfc,0xbda2bdc6,0xbdbebdac,0xbddf3d7c,0x3d4fbdea,0x3c493dff,0x3cf93df8,0x3dff3c17,0xbdd83d89,0x3d71bde2,0x3d2cbdf1,0xbdcabd9d,0x3e003b49,
0x3db53d80,0xbdf1bd2c,0xbd893dd8,0x3c7bbdfe,0x3d71bde2,0xbc963dfd,0x3def3d38,0xbdff3c17,0xbdf5bd15,0x3e00bbc9,0x3cafbdfc,0x3d093df7,0xbc493dff,0xbcf9bdf8,0xbe003b49,0x3de5bd66,
0xbdb53d80,0x3ddc3d84,0x3d9dbdca,0xbd4f3dea,0x3dff3c49,0x3de7bd5b,0xbd21bdf3,0x3d893dd8,0x3da2bdc6,0x3c96bdfd,0xbdf7bd09,0x3e003b49,0xbd15bdf5,0xbdbebdac,0xbdc23da7,0x3d93bdd1,
0x3db53d80,0xbdbebdac,0xbdb13db9,0x3da7bdc2,0x3d153df5,0xbddcbd84,0xbd893dd8,0x3d7cbddf,0x3d713de2,0xbdf1bd2c,0xbd383def,0x3d21bdf3,0x3da23dc6,0xbdfdbc96,0xbcaf3dfc,0x3c7bbdfe,
0xbdb53d80,0x3d983dce,0x3dc2bda7,0xbdd83d89,0xbdc63da2,0x3bc93e00,0x3dfebc7b,0xbe00bb49,0xbdff3c49,0xbd843ddc,0x3de53d66,0xbdd1bd93,0xbde2bd71,0xbde73d5b,0x3d7c3ddf,0xbd38bdef,
0x3db53d80,0xbd5bbde7,0xbdd13d93,0x3df7bd09,0xbde2bd71,0x3dcebd98,0xbdb9bdb1,0x3d663de5,0x3d15bdf5,0x3dbe3dac,0x3d89bdd8,0xbdca3d9d,0x3dff3c49,0xbd843ddc,0x3def3d38,0xbdc2bda7,
0xbdb53d80,0x3cf93df8,0x3ddfbd7c,0xbe00bb49,0x3c49bdff,0xbdf1bd2c,0xbc173dff,0x3d93bdd1,0x3dc63da2,0x3dcebd98,0xbdcabd9d,0x3d383def,0xbdf53d15,0x3bc93e00,0x3df3bd21,0xbdfabce0,
0x3db53d80,0xbbc9be00,0xbdea3d4f,0x3df33d21,0x3df5bd15,0x3cf93df8,0x3dd1bd93,0xbdfebc7b,0xbde23d71,0xbd5bbde7,0xbdb13db9,0x3dffbc17,0x3dc6bda2,0x3d983dce,0x3d89bdd8,0xbdf73d09,
0xbdb53d80,0xbc963dfd,0x3df3bd21,0xbdd1bd93,0x3da23dc6,0x3dacbdbe,0xbdf7bd09,0x3d383def,0xbc49bdff,0xbdf83cf9,0x3da73dc2,0x3ce0bdfa,0xbd713de2,0x3df13d2c,0xbc7bbdfe,0xbdb93db1,
0x3db53d80,0x3d2cbdf1,0xbdfa3ce0,0x3d9d3dca,0xbd713de2,0xbdfdbc96,0x3d4f3dea,0x3da7bdc2,0x3df53d15,0x3bc93e00,0x3dd1bd93,0xbddfbd7c,0x3c49bdff,0x3df8bcf9,0xbdb9bdb1,0xbd213df3,
0xbdb53d80,0xbd843ddc,0x3dfebc7b,0xbd38bdef,0xbdffbc49,0x3d5b3de7,0x3d66bde5,0xbdfabce0,0xbda23dc6,0x3dfd3c96,0xbd7cbddf,0xbdb93db1,0x3d153df5,0x3dacbdbe,0xbdffbc17,0x3caf3dfc,
0x3db53d80,0x3dacbdbe,0xbe003b49,0x3c173dff,0xbd15bdf5,0x3d84bddc,0xbdfa3ce0,0x3d093df7,0xbd71bde2,0x3d2cbdf1,0xbdea3d4f,0x3d663de5,0xbda2bdc6,0x3c96bdfd,0xbdd13d93,0x3d9d3dca,
0xbdb53d80,0xbdce3d98,0x3dff3c17,0x3ce0bdfa,0x3dc6bda2,0xbe003bc9,0x3dca3d9d,0x3db9bdb1,0x3dffbc49,0xbddcbd84,0x3d213df3,0x3dfcbcaf,0x3de23d71,0xbd5bbde7,0xbd093df7,0x3dea3d4f,
0x3db53d80,0x3de7bd5b,0xbdfcbcaf,0xbd7c3ddf,0x3de23d71,0x3d983dce,0xbb49be00,0xbdf3bd21,0xbd153df5,0xbdac3dbe,0x3dfabce0,0x3c7bbdfe,0xbdffbc49,0xbddcbd84,0x3d4f3dea,0x3dffbc17,
0xbdb53d80,0xbdf83cf9,0x3df73d09,0x3db9bdb1,0xbc493dff,0x3d2cbdf1,0xbdc23da7,0x3caf3dfc,0xbdc6bda2,0x3d983dce,0xbc7bbdfe,0xbdeabd4f,0x3df5bd15,0xbe003bc9,0x3de53d66,0x3dd8bd89,
0x3db53d80,0x3e00bbc9,0xbdefbd38,0xbde53d66,0xbdf53d15,0xbdf83cf9,0x3dfc3caf,0x3dcabd9d,0x3de2bd71,0x3de7bd5b,0xbe003b49,0xbda73dc2,0xbdc63da2,0xbdce3d98,0x3dfabce0,0x3d7cbddf,
0xbdb53d80,0xbdfdbc96,0x3de53d66,0x3dfcbcaf,0xbda2bdc6,0x3dbe3dac,0xbd7cbddf,0xbdeabd4f,0x3c493dff,0xbcf9bdf8,0xbc173dff,0x3d893dd8,0x3d71bde2,0xbd2c3df1,0x3d9dbdca,0x3b49be00,
0x3db53d80,0x3df13d2c,0xbdd8bd89,0xbdfebc7b,0x3d71bde2,0x3c96bdfd,0xbd383def,0x3c173dff,0xbdf5bd15,0xbe003bc9,0x3dfc3caf,0x3df7bd09,0xbc493dff,0x3cf93df8,0xbb49be00,0xbd66bde5,
0xbdb53d80,0xbddcbd84,0x3dca3d9d,0x3dea3d4f,0x3dff3c49,0xbde73d5b,0x3df3bd21,0x3dd8bd89,0x3da2bdc6,0xbc963dfd,0x3d09bdf7,0x3b49be00,0xbd15bdf5,0x3dbe3dac,0xbda7bdc2,0xbdd1bd93,
0x3db53d80,0x3dbe3dac,0xbdb9bdb1,0xbdc2bda7,0x3d153df5,0x3ddc3d84,0xbdd8bd89,0xbddfbd7c,0x3d713de2,0x3df13d2c,0xbdefbd38,0xbdf3bd21,0x3da23dc6,0x3dfd3c96,0xbdfcbcaf,0xbdfebc7b,
0x3f800000,0x0,0x3f800000,0x0,0x3f800000,0x0,0x3f800000,0x0,0x3f800000,0x0,0x3f800000,0x0,0x3f800000,0x0,0x3f800000,0x0,
0x3f800000,0x0,0x3f7ffb11,0xbc490e90,0x3f7fec43,0xbcc90ab0,0x3f7fd397,0xbd16c32c,0x3f7fb10f,0xbd48fb30,0x3f7f84ab,0xbd7b2b74,0x3f7f4e6d,0xbd96a905,0x3f7f0e58,0xbdafb680,
0x3f800000,0x0,0x3f7fec43,0xbcc90ab0,0x3f7fb10f,0xbd48fb30,0x3f7f4e6d,0xbd96a905,0x3f7ec46d,0xbdc8bd36,0x3f7e1324,0xbdfab273,0x3f7d3aac,0xbe164083,0x3f7c3b28,0xbe2f10a2,
0x3f800000,0x0,0x3f7fd397,0xbd16c32c,0x3f7f4e6d,0xbd96a905,0x3f7e70b0,0xbde1bc2e,0x3f7d3aac,0xbe164083,0x3f7baccd,0xbe3b6ecf,0x3f79c79d,0xbe605c13,0x3f778bc5,0xbe827dc0,
0x3f800000,0x0,0x3f7fb10f,0xbd48fb30,0x3f7ec46d,0xbdc8bd36,0x3f7d3aac,0xbe164083,0x3f7b14be,0xbe47c5c2,0x3f7853f8,0xbe78cfcc,0x3f74fa0b,0xbe94a031,0x3f710908,0xbeac7cd4,
0x3f800000,0x0,0x3f7f84ab,0xbd7b2b74,0x3f7e1324,0xbdfab273,0x3f7baccd,0xbe3b6ecf,0x3f7853f8,0xbe78cfcc,0x3f740bdd,0xbe9aa086,0x3f6ed89e,0xbeb8442a,0x3f68bf3c,0xbed53641,
0x3f800000,0x0,0x3f7f4e6d,0xbd96a905,0x3f7d3aac,0xbe164083,0x3f79c79d,0xbe605c13,0x3f74fa0b,0xbe94a031,0x3f6ed89e,0xbeb8442a,0x3f676bd8,0xbedae880,0x3f5ebe05,0xbefc5d27,
0x3f800000,0x0,0x3f7f0e58,0xbdafb680,0x3f7c3b28,0xbe2f10a2,0x3f778bc5,0xbe827dc0,0x3f710908,0xbeac7cd4,0x3f68bf3c,0xbed53641,0x3f5ebe05,0xbefc5d27,0x3f531849,0xbf10d3cd,
0x3f800000,0x0,0x3f7b14be,0xbe47c5c2,0x3f6c835e,0xbec3ef15,0x3f54db31,0xbf0e39da,0x3f3504f3,0xbf3504f3,0x3f0e39da,0xbf54db31,0x3ec3ef15,0xbf6c835e,0x3e47c5c2,0xbf7b14be,
0x3f800000,0x0,0x3f7a7302,0xbe541501,0x3f6a09a7,0xbecf7bca,0x3f4f7a1f,0xbf15f6d9,0x3f2beb4a,0xbf3daef9,0x3f00e7e4,0xbf5d2d53,0x3ea09ae5,0xbf731447,0x3de1bc2e,0xbf7e70b0,
0x3f800000,0x0,0x3f79c79d,0xbe605c13,0x3f676bd8,0xbedae880,0x3f49d112,0xbf1d7fd1,0x3f226799,0xbf45e403,0x3ee63375,0xbf64aa59,0x3e78cfcc,0xbf7853f8,0x3cc90ab0,0xbf7fec43,
0x3f800000,0x0,0x3f791298,0xbe6c9a7f,0x3f64aa59,0xbee63375,0x3f43e200,0xbf24d225,0x3f187fc0,0xbf4d9f02,0x3ec9b953,0xbf6b4b0c,0x3e2f10a2,0xbf7c3b28,0xbd7b2b74,0xbf7f84ab,
0x3f800000,0x0,0x3f7853f8,0xbe78cfcc,0x3f61c598,0xbef15aea,0x3f3daef9,0xbf2beb4a,0x3f0e39da,0xbf54db31,0x3eac7cd4,0xbf710908,0x3dc8bd36,0xbf7ec46d,0xbe164083,0xbf7d3aac,
0x3f800000,0x0,0x3f778bc5,0xbe827dc0,0x3f5ebe05,0xbefc5d27,0x3f373a23,0xbf32c8c9,0x3f039c3d,0xbf5b941a,0x3e8e9a22,0xbf75dec6,0x3cc90ab0,0xbf7fec43,0xbe6c9a7f,0xbf791298,
0x3f800000,0x0,0x3f76ba07,0xbe888e93,0x3f5b941a,0xbf039c3d,0x3f3085bb,0xbf396842,0x3ef15aea,0xbf61c598,0x3e605c13,0xbf79c79d,0xbd48fb30,0xbf7fb10f,0xbea09ae5,0xbf731447,
0x3f800000,0x0,0x3f75dec6,0xbe8e9a22,0x3f584853,0xbf08f59b,0x3f299415,0xbf3fc767,0x3edae880,0xbf676bd8,0x3e22abb6,0xbf7cbfc9,0xbdfab273,0xbf7e1324,0xbec9b953,0xbf6b4b0c,
0x3f800000,0x0,0x3f7ec46d,0xbdc8bd36,0x3f7b14be,0xbe47c5c2,0x3f74fa0b,0xbe94a031,0x3f6c835e,0xbec3ef15,0x3f61c598,0xbef15aea,0x3f54db31,0xbf0e39da,0x3f45e403,0xbf226799,
0x3f800000,0x0,0x3f6b4b0c,0xbec9b953,0x3f3085bb,0xbf396842,0x3eb263ef,0xbf6ff573,0xbd48fb30,0xbf7fb10f,0xbee0924f,0xbf660f88,0xbf41d870,0xbf273656,0xbf740bdd,0xbe9aa086,
0x3f800000,0x0,0x3f6a09a7,0xbecf7bca,0x3f2beb4a,0xbf3daef9,0x3ea09ae5,0xbf731447,0xbdc8bd36,0xbf7ec46d,0xbefc5d27,0xbf5ebe05,0xbf4d9f02,0xbf187fc0,0xbf79c79d,0xbe605c13,
0x3f800000,0x0,0x3f68bf3c,0xbed53641,0x3f273656,0xbf41d870,0x3e8e9a22,0xbf75dec6,0xbe164083,0xbf7d3aac,0xbf0b9a6b,0xbf5695e5,0xbf584853,0xbf08f59b,0xbf7dabcc,0xbe09cf86,
0x3f800000,0x0,0x3f676bd8,0xbedae880,0x3f226799,0xbf45e403,0x3e78cfcc,0xbf7853f8,0xbe47c5c2,0xbf7b14be,0xbf187fc0,0xbf4d9f02,0xbf61c598,0xbef15aea,0xbf7fb10f,0xbd48fb30,
0x3f800000,0x0,0x3f660f88,0xbee0924f,0x3f1d7fd1,0xbf49d112,0x3e541501,0xbf7a7302,0xbe78cfcc,0xbf7853f8,0xbf24d225,0xbf43e200,0xbf6a09a7,0xbecf7bca,0xbf7fd397,0x3d16c32c,
0x3f800000,0x0,0x3f64aa59,0xbee63375,0x3f187fc0,0xbf4d9f02,0x3e2f10a2,0xbf7c3b28,0xbe94a031,0xbf74fa0b,0xbf3085bb,0xbf396842,0xbf710908,0xbeac7cd4,0xbf7e1324,0x3dfab273,
0x3f800000,0x0,0x3f633c5a,0xbeebcbbb,0x3f13682a,0xbf514d3d,0x3e09cf86,0xbf7dabcc,0xbeac7cd4,0xbf710908,0xbf3b8f3b,0xbf2e3bde,0xbf76ba07,0xbe888e93,0xbf7a7302,0x3e541501,
0x3f800000,0x0,0x3f74fa0b,0xbe94a031,0x3f54db31,0xbf0e39da,0x3f226799,0xbf45e403,0x3ec3ef15,0xbf6c835e,0x3dc8bd36,0xbf7ec46d,0xbe47c5c2,0xbf7b14be,0xbef15aea,0xbf61c598,
0x3f800000,0x0,0x3f531849,0xbf10d3cd,0x3eb8442a,0xbf6ed89e,0xbe6c9a7f,0xbf791298,0xbf3daef9,0xbf2beb4a,0xbf7dabcc,0xbe09cf86,0xbf64aa59,0x3ee63375,0xbef6e0cb,0x3f604621,
0x3f800000,0x0,0x3f514d3d,0xbf13682a,0x3eac7cd4,0xbf710908,0xbe888e93,0xbf76ba07,0xbf45e403,0xbf226799,0xbf7f4e6d,0xbd96a905,0xbf5b941a,0x3f039c3d,0xbecf7bca,0x3f6a09a7,
0x3f800000,0x0,0x3f4f7a1f,0xbf15f6d9,0x3ea09ae5,0xbf731447,0xbe9aa086,0xbf740bdd,0xbf4d9f02,0xbf187fc0,0xbf7ffb11,0xbc490e90,0xbf514d3d,0x3f13682a,0xbea68f12,0x3f721352,
0x3f800000,0x0,0x3f4d9f02,0xbf187fc0,0x3e94a031,0xbf74fa0b,0xbeac7cd4,0xbf710908,0xbf54db31,0xbf0e39da,0xbf7fb10f,0x3d48fb30,0xbf45e403,0x3f226799,0xbe78cfcc,0x3f7853f8,
0x3f800000,0x0,0x3f4bbbf8,0xbf1b02c6,0x3e888e93,0xbf76ba07,0xbebe1d4a,0xbf6db293,0xbf5b941a,0xbf039c3d,0xbf7e70b0,0x3de1bc2e,0xbf396842,0x3f3085bb,0xbe22abb6,0x3f7cbfc9,
0x3f800000,0x0,0x3f49d112,0xbf1d7fd1,0x3e78cfcc,0xbf7853f8,0xbecf7bca,0xbf6a09a7,0xbf61c598,0xbef15aea,0xbf7c3b28,0x3e2f10a2,0xbf2beb4a,0x3f3daef9,0xbd96a905,0x3f7f4e6d,
0x3f800000,0x0,0x3f47de65,0xbf1ff6cb,0x3e605c13,0xbf79c79d,0xbee0924f,0xbf660f88,0xbf676bd8,0xbedae880,0xbf791298,0x3e6c9a7f,0xbf1d7fd1,0x3f49d112,0x3c490e90,0x3f7ffb11,
0x3f800000,0x0,0x3f800000,0x0,0x3f800000,0x0,0x3f800000,0x0,0x40000000,0x0,0x3f800000,0x0,0x3f800000,0x0,0x3f800000,0x0,
0x3f800000,0x0,0x3f7ffb11,0xbc490e90,0x3f7fec43,0xbcc90ab0,0x3f7fd397,0xbd16c32c,0x3fffb10f,0xbdc8fb30,0x3f7f84ab,0xbd7b2b74,0x3f7f4e6d,0xbd96a905,0x3f7f0e58,0xbdafb680,
0x3f800000,0x0,0x3f7fec43,0xbcc90ab0,0x3f7fb10f,0xbd48fb30,0x3f7f4e6d,0xbd96a905,0x3ffec46d,0xbe48bd36,0x3f7e1324,0xbdfab273,0x3f7d3aac,0xbe164083,0x3f7c3b28,0xbe2f10a2,
0x3f800000,0x0,0x3f7fd397,0xbd16c32c,0x3f7f4e6d,0xbd96a905,0x3f7e70b0,0xbde1bc2e,0x3ffd3aac,0xbe964083,0x3f7baccd,0xbe3b6ecf,0x3f79c79d,0xbe605c13,0x3f778bc5,0xbe827dc0,
0x3f800000,0x0,0x3f7fb10f,0xbd48fb30,0x3f7ec46d,0xbdc8bd36,0x3f7d3aac,0xbe164083,0x3ffb14be,0xbec7c5c2,0x3f7853f8,0xbe78cfcc,0x3f74fa0b,0xbe94a031,0x3f710908,0xbeac7cd4,
0x3f800000,0x0,0x3f7f84ab,0xbd7b2b74,0x3f7e1324,0xbdfab273,0x3f7baccd,0xbe3b6ecf,0x3ff853f8,0xbef8cfcc,0x3f740bdd,0xbe9aa086,0x3f6ed89e,0xbeb8442a,0x3f68bf3c,0xbed53641,
0x3f800000,0x0,0x3f7f4e6d,0xbd96a905,0x3f7d3aac,0xbe164083,0x3f79c79d,0xbe605c13,0x3ff4fa0b,0xbf14a031,0x3f6ed89e,0xbeb8442a,0x3f676bd8,0xbedae880,0x3f5ebe05,0xbefc5d27,
0x3f800000,0x0,0x3f7f0e58,0xbdafb680,0x3f7c3b28,0xbe2f10a2,0x3f778bc5,0xbe827dc0,0x3ff10908,0xbf2c7cd4,0x3f68bf3c,0xbed53641,0x3f5ebe05,0xbefc5d27,0x3f531849,0xbf10d3cd,
0x3f800000,0x0,0x3f7ec46d,0xbdc8bd36,0x3f7b14be,0xbe47c5c2,0x3f74fa0b,0xbe94a031,0x3fec835e,0xbf43ef15,0x3f61c598,0xbef15aea,0x3f54db31,0xbf0e39da,0x3f45e403,0xbf226799,
0x3f800000,0x0,0x3f7e70b0,0xbde1bc2e,0x3f79c79d,0xbe605c13,0x3f721352,0xbea68f12,0x3fe76bd8,0xbf5ae880,0x3f59f26a,0xbf064b82,0x3f49d112,0xbf1d7fd1,0x3f373a23,0xbf32c8c9,
0x3f800000,0x0,0x3f7e1324,0xbdfab273,0x3f7853f8,0xbe78cfcc,0x3f6ed89e,0xbeb8442a,0x3fe1c598,0xbf715aea,0x3f514d3d,0xbf13682a,0x3f3daef9,0xbf2beb4a,0x3f273656,0xbf41d870,
0x3f800000,0x0,0x3f7dabcc,0xbe09cf86,0x3f76ba07,0xbe888e93,0x3f6b4b0c,0xbec9b953,0x3fdb941a,0xbf839c3d,0x3f47de65,0xbf1ff6cb,0x3f3085bb,0xbf396842,0x3f15f6d9,0xbf4f7a1f,
0x3f800000,0x0,0x3f7d3aac,0xbe164083,0x3f74fa0b,0xbe94a031,0x3f676bd8,0xbedae880,0x3fd4db31,0xbf8e39da,0x3f3daef9,0xbf2beb4a,0x3f226799,0xbf45e403,0x3f039c3d,0xbf5b941a,
0x3f800000,0x0,0x3f7cbfc9,0xbe22abb6,0x3f731447,0xbea09ae5,0x3f633c5a,0xbeebcbbb,0x3fcd9f02,0xbf987fc0,0x3f32c8c9,0xbf373a23,0x3f13682a,0xbf514d3d,0x3ee0924f,0xbf660f88,
0x3f800000,0x0,0x3f7c3b28,0xbe2f10a2,0x3f710908,0xbeac7cd4,0x3f5ebe05,0xbefc5d27,0x3fc5e403,0xbfa26799,0x3f273656,0xbf41d870,0x3f039c3d,0xbf5b941a,0x3eb8442a,0xbf6ed89e,
0x3f800000,0x0,0x3f7baccd,0xbe3b6ecf,0x3f6ed89e,0xbeb8442a,0x3f59f26a,0xbf064b82,0x3fbdaef9,0xbfabeb4a,0x3f1b02c6,0xbf4bbbf8,0x3ee63375,0xbf64aa59,0x3e8e9a22,0xbf75dec6,
0x3f800000,0x0,0x3f7b14be,0xbe47c5c2,0x3f6c835e,0xbec3ef15,0x3f54db31,0xbf0e39da,0x3fb504f3,0xbfb504f3,0x3f0e39da,0xbf54db31,0x3ec3ef15,0xbf6c835e,0x3e47c5c2,0xbf7b14be,
0x3f800000,0x0,0x3f7a7302,0xbe541501,0x3f6a09a7,0xbecf7bca,0x3f4f7a1f,0xbf15f6d9,0x3fabeb4a,0xbfbdaef9,0x3f00e7e4,0xbf5d2d53,0x3ea09ae5,0xbf731447,0x3de1bc2e,0xbf7e70b0,
0x3f800000,0x0,0x3f79c79d,0xbe605c13,0x3f676bd8,0xbedae880,0x3f49d112,0xbf1d7fd1,0x3fa26799,0xbfc5e403,0x3ee63375,0xbf64aa59,0x3e78cfcc,0xbf7853f8,0x3cc90ab0,0xbf7fec43,
0x3f800000,0x0,0x3f791298,0xbe6c9a7f,0x3f64aa59,0xbee63375,0x3f43e200,0xbf24d225,0x3f987fc0,0xbfcd9f02,0x3ec9b953,0xbf6b4b0c,0x3e2f10a2,0xbf7c3b28,0xbd7b2b74,0xbf7f84ab,
0x3f800000,0x0,0x3f7853f8,0xbe78cfcc,0x3f61c598,0xbef15aea,0x3f3daef9,0xbf2beb4a,0x3f8e39da,0xbfd4db31,0x3eac7cd4,0xbf710908,0x3dc8bd36,0xbf7ec46d,0xbe164083,0xbf7d3aac,
0x3f800000,0x0,0x3f778bc5,0xbe827dc0,0x3f5ebe05,0xbefc5d27,0x3f373a23,0xbf32c8c9,0x3f839c3d,0xbfdb941a,0x3e8e9a22,0xbf75dec6,0x3cc90ab0,0xbf7fec43,0xbe6c9a7f,0xbf791298,
0x3f800000,0x0,0x3f76ba07,0xbe888e93,0x3f5b941a,0xbf039c3d,0x3f3085bb,0xbf396842,0x3f715aea,0xbfe1c598,0x3e605c13,0xbf79c79d,0xbd48fb30,0xbf7fb10f,0xbea09ae5,0xbf731447,
0x3f800000,0x0,0x3f75dec6,0xbe8e9a22,0x3f584853,0xbf08f59b,0x3f299415,0xbf3fc767,0x3f5ae880,0xbfe76bd8,0x3e22abb6,0xbf7cbfc9,0xbdfab273,0xbf7e1324,0xbec9b953,0xbf6b4b0c,
0x3f800000,0x0,0x3f74fa0b,0xbe94a031,0x3f54db31,0xbf0e39da,0x3f226799,0xbf45e403,0x3f43ef15,0xbfec835e,0x3dc8bd36,0xbf7ec46d,0xbe47c5c2,0xbf7b14be,0xbef15aea,0xbf61c598,
0x3f800000,0x0,0x3f740bdd,0xbe9aa086,0x3f514d3d,0xbf13682a,0x3f1b02c6,0xbf4bbbf8,0x3f2c7cd4,0xbff10908,0x3d16c32c,0xbf7fd397,0xbe888e93,0xbf76ba07,0xbf0b9a6b,0xbf5695e5,
0x3f800000,0x0,0x3f731447,0xbea09ae5,0x3f4d9f02,0xbf187fc0,0x3f13682a,0xbf514d3d,0x3f14a031,0xbff4fa0b,0xbcc90ab0,0xbf7fec43,0xbeac7cd4,0xbf710908,0xbf1d7fd1,0xbf49d112,
0x3f800000,0x0,0x3f721352,0xbea68f12,0x3f49d112,0xbf1d7fd1,0x3f0b9a6b,0xbf5695e5,0x3ef8cfcc,0xbff853f8,0xbdafb680,0xbf7f0e58,0xbecf7bca,0xbf6a09a7,0xbf2e3bde,0xbf3b8f3b,
0x3f800000,0x0,0x3f710908,0xbeac7cd4,0x3f45e403,0xbf226799,0x3f039c3d,0xbf5b941a,0x3ec7c5c2,0xbffb14be,0xbe164083,0xbf7d3aac,0xbef15aea,0xbf61c598,0xbf3daef9,0xbf2beb4a,
0x3f800000,0x0,0x3f6ff573,0xbeb263ef,0x3f41d870,0xbf273656,0x3ef6e0cb,0xbf604621,0x3e964083,0xbffd3aac,0xbe541501,0xbf7a7302,0xbf08f59b,0xbf584853,0xbf4bbbf8,0xbf1b02c6,
0x3f800000,0x0,0x3f6ed89e,0xbeb8442a,0x3f3daef9,0xbf2beb4a,0x3ee63375,0xbf64aa59,0x3e48bd36,0xbffec46d,0xbe888e93,0xbf76ba07,0xbf187fc0,0xbf4d9f02,0xbf584853,0xbf08f59b,
0x3f800000,0x0,0x3f6db293,0xbebe1d4a,0x3f396842,0xbf3085bb,0x3ed53641,0xbf68bf3c,0x3dc8fb30,0xbfffb10f,0xbea68f12,0xbf721352,0xbf273656,0xbf41d870,0xbf633c5a,0xbeebcbbb,
0x3f800000,0x0,0x3f7fffb1,0xbb490fc6,0x3f7ffec4,0xbbc90f88,0x3f7ffd39,0xbc16cb58,0x3ffffb11,0xbcc90e90,0x3f7ff84a,0xbc7b514b,0x3f7ff4e6,0xbc96c9b6,0x3f7ff0e3,0xbcafea69,
0x3f800000,0x0,0x3f7ff84a,0xbc7b514b,0x3f7fe129,0xbcfb49ba,0x3f7fba9e,0xbd3c6dd5,0x3fff84ab,0xbdfb2b74,0x3f7f3f54,0xbd9cecf9,0x3f7eea9d,0xbdbc3ac3,0x3f7e868b,0xbddb7d37,
0x3f800000,0x0,0x3f7fe705,0xbce22a7a,0x3f7f9c18,0xbd621469,0x3f7f1f49,0xbda973ba,0x3ffe70b0,0xbe61bc2e,0x3f7d906e,0xbe0cec4a,0x3f7c7eb0,0xbe28defc,0x3f7b3bab,0xbe44b0b9,
0x3f800000,0x0,0x3f7fcbe2,0xbd2351cb,0x3f7f2f9d,0xbda3308c,0x3f7e2b72,0xbdf475c0,0x3ffcbfc9,0xbea2abb6,0x3f7aed37,0xbe4ada4f,0x3f78b47b,0xbe72b651,0x3f76167a,0xbe8d17c0,
0x3f800000,0x0,0x3f7fa6e3,0xbd55880e,0x3f7e9bc9,0xbdd53db9,0x3f7cdf6c,0xbe1f917b,0x3ffa7302,0xbed41501,0x3f77583a,0xbe840270,0x3f73913f,0xbe9d9e78,0x3f6f20b0,0xbeb6ccc3,
0x3f800000,0x0,0x3f7f7808,0xbd83db0a,0x3f7de0b1,0xbe039502,0x3f7b3bab,0xbe44b0b9,0x3ff78bc5,0xbf027dc0,0x3f72d4eb,0xbea21887,0x3f6d1c1d,0xbec1071e,0x3f666771,0xbedf28a9,
0x3f800000,0x0,0x3f7f3f54,0xbd9cecf9,0x3f7cfe73,0xbe1c76de,0x3f7940c0,0xbe698bba,0x3ff40bdd,0xbf1aa086,0x3f6d67a1,0xbebf926f,0x3f655e0b,0xbee363fa,0x3f5bfb34,0xbf02ef9f,
0x3f800000,0x0,0x3f7efcc9,0xbdb5f8da,0x3f7bf531,0xbe354098,0x3f76ef5b,0xbe870ada,0x3feff573,0xbf3263ef,0x3f671599,0xbedc53c1,0x3f5c61c7,0xbf0242b1,0x3f4fefa8,0xbf1553b7,
0x3f800000,0x0,0x3f7eb069,0xbdcefdb7,0x3f7ac516,0xbe4dee60,0x3f74484b,0xbe9920fe,0x3feb4b0c,0xbf49b953,0x3f5fe4e9,0xbef840c8,0x3f5233c6,0xbf121eb0,0x3f425b89,0xbf269de3,
0x3f800000,0x0,0x3f7e5a38,0xbde7fa9a,0x3f796e4e,0xbe667c66,0x3f714c7a,0xbeab0201,0x3fe60f88,0xbf60924f,0x3f57dc7f,0xbf099f4e,0x3f46e22a,0xbf212ff9,0x3f33587a,0xbf36ad7f,
0x3f800000,0x0,0x3f7dfa38,0xbe007745,0x3f77f110,0xbe7ee6e1,0x3f6dfcf2,0xbebca7af,0x3fe04621,0xbf76e0cb,0x3f4f0417,0xbf16999f,0x3f3a7ca4,0xbf2f61a5,0x3f2302d3,0xbf456439,
0x3f800000,0x0,0x3f7d906e,0xbe0cec4a,0x3f764d97,0xbe8b9507,0x3f6a5ad9,0xbece0bea,0x3fd9f26a,0xbf864b82,0x3f456439,0xbf2302d3,0x3f2d1469,0xbf3ca003,0x3f11796b,0xbf52a649,
0x3f800000,0x0,0x3f7d1cdd,0xbe195be0,0x3f748422,0xbe97a117,0x3f666771,0xbedf28a9,0x3fd31849,0xbf90d3cd,0x3f3b0629,0xbf2ecef7,0x3f1ebc12,0xbf48d8b3,0x3efdbabb,0xbf5e5aa6,
0x3f800000,0x0,0x3f7c9f8a,0xbe25c58c,0x3f7294f8,0xbea395c5,0x3f62241a,0xbeeff7fb,0x3fcbbbf8,0xbf9b02c6,0x3f2ff3e6,0xbf39f2ac,0x3f0f8784,0xbf53fac3,0x3ed6a399,0xbf686b39,
0x3f800000,0x0,0x3f7c187a,0xbe3228d4,0x3f708066,0xbeaf713a,0x3f5d924d,0xbf003a06,0x3fc3e200,0xbfa4d225,0x3f24381a,0xbf446337,0x3eff17b2,0xbf5df6be,0x3eadf73c,0xbf70c501,
0x3f800000,0x0,0x3f7b87b2,0xbe3e853e,0x3f6e46be,0xbebb31a0,0x3f58b3a1,0xbf084b92,0x3fbb8f3b,0xbfae3bde,0x3f17de12,0xbf4e1689,0x3eddbe79,0xbf66becc,0x3e840270,0xbf77583a,
0x3f800000,0x0,0x3f7aed37,0xbe4ada4f,0x3f6be858,0xbec6d529,0x3f5389c7,0xbf102dd5,0x3fb2c8c9,0xbfb73a23,0x3f0af1b7,0xbf570348,0x3ebb31a0,0xbf6e46be,0x3e3228d4,0xbf7c187a,
0x3f800000,0x0,0x3f7a4910,0xbe57278f,0x3f696591,0xbed25a09,0x3f4e1689,0xbf17de12,0x3fa99415,0xbfbfc767,0x3efafef7,0xbf5f20db,0x3e97a117,0xbf748422,0x3db5f8da,0xbf7efcc9,
0x3f800000,0x0,0x3f799b43,0xbe636c83,0x3f66becc,0xbeddbe79,0x3f485bca,0xbf1f599f,0x3f9ff6cb,0xbfc7de65,0x3edf28a9,0xbf666771,0x3e667c66,0xbf796e4e,0x3b490fc6,0xbf7fffb1,
0x3f800000,0x0,0x3f78e3d6,0xbe6fa8b2,0x3f63f473,0xbee900b7,0x3f425b89,0xbf269de3,0x3f95f6d9,0xbfcf7a1f,0x3ec27b55,0xbf6cd007,0x3e1c76de,0xbf7cfe73,0xbda973ba,0xbf7f1f49,
0x3f800000,0x0,0x3f7822d1,0xbe7bdba4,0x3f6106f2,0xbef41f07,0x3f3c17d9,0xbf2da859,0x3f8b9a6b,0xbfd695e5,0x3ea5129f,0xbf725470,0x3da3308c,0xbf7f2f9d,0xbe2bf804,0xbf7c5d3a,
0x3f800000,0x0,0x3f77583a,0xbe840270,0x3f5df6be,0xbeff17b2,0x3f3592e7,0xbf34768f,0x3f80e7e4,0xbfdd2d53,0x3e870ada,0xbf76ef5b,0x3bc90f88,0xbf7ffec4,0xbe80f8c0,0xbf77beb7,
0x3f800000,0x0,0x3f76841b,0xbe8a11f7,0x3f5ac450,0xbf04f484,0x3f2ecef7,0xbf3b0629,0x3f6bcbbb,0xbfe33c5a,0x3e5101f1,0xbf7a9c59,0xbd8a200a,0xbf7f6ac7,0xbeab0201,0xbf714c7a,
0x3f800000,0x0,0x3f75a67b,0xbe901c2c,0x3f577026,0xbf0a48ad,0x3f27ce61,0xbf4154e1,0x3f553641,0xbfe8bf3c,0x3e1324ca,0xbf7d57de,0xbe1008b7,0xbf7d7474,0xbed3c867,0xbf6912ae,
0x3f800000,0x0,0x3f74bf62,0xbe9620d2,0x3f53fac3,0xbf0f8784,0x3f209393,0xbf476085,0x3f3e1d4a,0xbfedb293,0x3da973ba,0xbf7f1f49,0xbe5a3997,0xbf7a1e84,0xbefafef7,0xbf5f20db,
0x3f800000,0x0,0x3f73ced9,0xbe9c1faf,0x3f5064af,0xbf14b039,0x3f19210f,0xbf4d26fd,0x3f268f12,0xbff21352,0x3cafea69,0xbf7ff0e3,0xbe919ddd,0xbf756d97,0xbf102dd5,0xbf5389c7,
0x3f800000,0x0,0x3f72d4eb,0xbea21887,0x3f4cae79,0xbf19c200,0x3f11796b,0xbf52a649,0x3f0e9a22,0xbff5dec6,0xbd2351cb,0xbf7fcbe2,0xbeb554ec,0xbf6f6830,0xbf21cbfb,0xbf466354,
0x3f800000,0x0,0x3f71d19f,0xbea80b1f,0x3f48d8b3,0xbf1ebc12,0x3f099f4e,0xbf57dc7f,0x3eec9a7f,0xbff91298,0xbdcefdb7,0xbf7eb069,0xbed8106b,0xbf6816a8,0xbf3238aa,0xbf37c655,
0x3f800000,0x0,0x3f70c501,0xbeadf73c,0x3f44e3f5,0xbf239da9,0x3f019573,0xbf5cc7d1,0x3ebb6ecf,0xbffbaccd,0xbe25c58c,0xbf7c9f8a,0xbef9a02d,0xbf5f8327,0xbf4154e1,0xbf27ce61,
0x3f800000,0x0,0x3f6faf1b,0xbeb3dca5,0x3f40d0da,0xbf286605,0x3ef2bd43,0xbf61668a,0x3e89cf86,0xbffdabcc,0xbe636c83,0xbf799b43,0xbf0cead0,0xbf55b993,0xbf4f0417,0xbf16999f,
0x3f800000,0x0,0x3f6e8ff8,0xbeb9bb1e,0x3f3ca003,0xbf2d1469,0x3ee1fb6a,0xbf65b710,0x3e2fb680,0xbfff0e58,0xbe901c2c,0xbf75a67b,0xbf1c420c,0xbf4ac77f,0xbf5b2c79,0xbf044889,
0x3f800000,0x0,0x3f6d67a1,0xbebf926f,0x3f385216,0xbf31a81d,0x3ed0eb2a,0xbf69b7e4,0x3d96c32c,0xbfffd397,0xbeadf73c,0xbf70c501,0xbf2ac082,0xbf3ebc1b,0xbf65b710,0xbee1fb6a,
0x3f800000,0x0,0x3f7ffec4,0xbbc90f88,0x3f7ffb11,0xbc490e90,0x3f7ff4e6,0xbc96c9b6,0x3fffec43,0xbd490ab0,0x3f7fe129,0xbcfb49ba,0x3f7fd397,0xbd16c32c,0x3f7fc38f,0xbd2fe007,
0x3f800000,0x0,0x3f7ff4e6,0xbc96c9b6,0x3f7fd397,0xbd16c32c,0x3f7f9c18,0xbd621469,0x3fff4e6d,0xbe16a905,0x3f7eea9d,0xbdbc3ac3,0x3f7e70b0,0xbde1bc2e,0x3f7de0b1,0xbe039502,
0x3f800000,0x0,0x3f7fe129,0xbcfb49ba,0x3f7f84ab,0xbd7b2b74,0x3f7eea9d,0xbdbc3ac3,0x3ffe1324,0xbe7ab273,0x3f7cfe73,0xbe1c76de,0x3f7baccd,0xbe3b6ecf,0x3f7a1e84,0xbe5a3997,
0x3f800000,0x0,0x3f7fc38f,0xbd2fe007,0x3f7f0e58,0xbdafb680,0x3f7de0b1,0xbe039502,0x3ffc3b28,0xbeaf10a2,0x3f7a1e84,0xbe5a3997,0x3f778bc5,0xbe827dc0,0x3f748422,0xbe97a117,
0x3f800000,0x0,0x3f7f9c18,0xbd621469,0x3f7e70b0,0xbde1bc2e,0x3f7c7eb0,0xbe28defc,0x3ff9c79d,0xbee05c13,0x3f764d97,0xbe8b9507,0x3f721352,0xbea68f12,0x3f6d1c1d,0xbec1071e,
0x3f800000,0x0,0x3f7f6ac7,0xbd8a200a,0x3f7dabcc,0xbe09cf86,0x3f7ac516,0xbe4dee60,0x3ff6ba07,0xbf088e93,0x3f718f57,0xbea986c4,0x3f6b4b0c,0xbec9b953,0x3f63f473,0xbee900b7,
0x3f800000,0x0,0x3f7f2f9d,0xbda3308c,0x3f7cbfc9,0xbe22abb6,0x3f78b47b,0xbe72b651,0x3ff31447,0xbf209ae5,0x3f6be858,0xbec6d529,0x3f633c5a,0xbeebcbbb,0x3f591e6a,0xbf07a136,
0x3f800000,0x0,0x3f7eea9d,0xbdbc3ac3,0x3f7baccd,0xbe3b6ecf,0x3f764d97,0xbe8b9507,0x3feed89e,0xbf38442a,0x3f655e0b,0xbee363fa,0x3f59f26a,0xbf064b82,0x3f4cae79,0xbf19c200,
0x3f800000,0x0,0x3f7e9bc9,0xbdd53db9,0x3f7a7302,0xbe541501,0x3f73913f,0xbe9d9e78,0x3fea09a7,0xbf4f7bca,0x3f5df6be,0xbeff17b2,0x3f4f7a1f,0xbf15f6d9,0x3f3ebc1b,0xbf2ac082,
0x3f800000,0x0,0x3f7e4323,0xbdee3876,0x3f791298,0xbe6c9a7f,0x3f708066,0xbeaf713a,0x3fe4aa59,0xbf663375,0x3f55b993,0xbf0cead0,0x3f43e200,0xbf24d225,0x3f2f61a5,0xbf3a7ca4,
0x3f800000,0x0,0x3f7de0b1,0xbe039502,0x3f778bc5,0xbe827dc0,0x3f6d1c1d,0xbec1071e,0x3fdebe05,0xbf7c5d27,0x3f4cae79,0xbf19c200,0x3f373a23,0xbf32c8c9,0x3f1ebc12,0xbf48d8b3,
0x3f800000,0x0,0x3f7d7474,0xbe1008b7,0x3f75dec6,0xbe8e9a22,0x3f696591,0xbed25a09,0x3fd84853,0xbf88f59b,0x3f42de29,0xbf26050a,0x3f299415,0xbf3fc767,0x3f0cead0,0xbf55b993,
0x3f800000,0x0,0x3f7cfe73,0xbe1c76de,0x3f740bdd,0xbe9aa086,0x3f655e0b,0xbee363fa,0x3fd14d3d,0xbf93682a,0x3f385216,0xbf31a81d,0x3f1b02c6,0xbf4bbbf8,0x3ef41f07,0xbf6106f2,
0x3f800000,0x0,0x3f7c7eb0,0xbe28defc,0x3f721352,0xbea68f12,0x3f6106f2,0xbef41f07,0x3fc9d112,0xbf9d7fd1,0x3f2d1469,0xbf3ca003,0x3f0b9a6b,0xbf5695e5,0x3ecc9b8b,0xbf6aab7b,
0x3f800000,0x0,0x3f7bf531,0xbe354098,0x3f6ff573,0xbeb263ef,0x3f5c61c7,0xbf0242b1,0x3fc1d870,0xbfa73656,0x3f212ff9,0xbf46e22a,0x3ef6e0cb,0xbf604621,0x3ea395c5,0xbf7294f8,
0x3f800000,0x0,0x3f7b61fc,0xbe419b37,0x3f6db293,0xbebe1d4a,0x3f577026,0xbf0a48ad,0x3fb96842,0xbfb085bb,0x3f14b039,0xbf5064af,0x3ed53641,0xbf68bf3c,0x3e72b651,0xbf78b47b,
0x3f800000,0x0,0x3f7ac516,0xbe4dee60,0x3f6b4b0c,0xbec9b953,0x3f5233c6,0xbf121eb0,0x3fb085bb,0xbfb96842,0x3f07a136,0xbf591e6a,0x3eb263ef,0xbf6ff573,0x3e1c76de,0xbf7cfe73,
0x3f800000,0x0,0x3f7a1e84,0xbe5a3997,0x3f68bf3c,0xbed53641,0x3f4cae79,0xbf19c200,0x3fa73656,0xbfc1d870,0x3ef41f07,0xbf6106f2,0x3e8e9a22,0xbf75dec6,0x3d8a200a,0xbf7f6ac7,
0x3f800000,0x0,0x3f796e4e,0xbe667c66,0x3f660f88,0xbee0924f,0x3f46e22a,0xbf212ff9,0x3f9d7fd1,0xbfc9d112,0x3ed8106b,0xbf6816a8,0x3e541501,0xbf7a7302,0xbc96c9b6,0xbf7ff4e6,
0x3f800000,0x0,0x3f78b47b,0xbe72b651,0x3f633c5a,0xbeebcbbb,0x3f40d0da,0xbf286605,0x3f93682a,0xbfd14d3d,0x3ebb31a0,0xbf6e46be,0x3e09cf86,0xbf7dabcc,0xbdd53db9,0xbf7e9bc9,
0x3f800000,0x0,0x3f77f110,0xbe7ee6e1,0x3f604621,0xbef6e0cb,0x3f3a7ca4,0xbf2f61a5,0x3f88f59b,0xbfd84853,0x3e9d9e78,0xbf73913f,0x3d7b2b74,0xbf7f84ab,0xbe419b37,0xbf7b61fc,
0x3f800000,0x0,0x3f772417,0xbe8586ce,0x3f5d2d53,0xbf00e7e4,0x3f33e7bc,0xbf36206c,0x3f7c5d27,0xbfdebe05,0x3e7ee6e1,0xbf77f110,0xbc490e90,0xbf7ffb11,0xbe8b9507,0xbf764d97,
0x3f800000,0x0,0x3f764d97,0xbe8b9507,0x3f59f26a,0xbf064b82,0x3f2d1469,0xbf3ca003,0x3f663375,0xbfe4aa59,0x3e419b37,0xbf7b61fc,0xbdafb680,0xbf7f0e58,0xbeb554ec,0xbf6f6830,
0x3f800000,0x0,0x3f756d97,0xbe919ddd,0x3f5695e5,0xbf0b9a6b,0x3f26050a,0xbf42de29,0x3f4f7bca,0xbfea09a7,0x3e039502,0xbf7de0b1,0xbe22abb6,0xbf7cbfc9,0xbeddbe79,0xbf66becc,
0x3f800000,0x0,0x3f748422,0xbe97a117,0x3f531849,0xbf10d3cd,0x3f1ebc12,0xbf48d8b3,0x3f38442a,0xbfeed89e,0x3d8a200a,0xbf7f6ac7,0xbe6c9a7f,0xbf791298,0xbf0242b1,0xbf5c61c7,
0x3f800000,0x0,0x3f73913f,0xbe9d9e78,0x3f4f7a1f,0xbf15f6d9,0x3f173c07,0xbf4e8d90,0x3f209ae5,0xbff31447,0x3bc90f88,0xbf7ffec4,0xbe9aa086,0xbf740bdd,0xbf14b039,0xbf5064af,
0x3f800000,0x0,0x3f7294f8,0xbea395c5,0x3f4bbbf8,0xbf1b02c6,0x3f0f8784,0xbf53fac3,0x3f088e93,0xbff6ba07,0xbd621469,0xbf7f9c18,0xbebe1d4a,0xbf6db293,0xbf26050a,0xbf42de29,
0x3f800000,0x0,0x3f718f57,0xbea986c4,0x3f47de65,0xbf1ff6cb,0x3f07a136,0xbf591e6a,0x3ee05c13,0xbff9c79d,0xbdee3876,0xbf7e4323,0xbee0924f,0xbf660f88,0xbf36206c,0xbf33e7bc,
0x3f800000,0x0,0x3f708066,0xbeaf713a,0x3f43e200,0xbf24d225,0x3eff17b2,0xbf5df6be,0x3eaf10a2,0xbffc3b28,0xbe354098,0xbf7bf531,0xbf00e7e4,0xbf5d2d53,0xbf44e3f5,0xbf239da9,
0x3f800000,0x0,0x3f6f6830,0xbeb554ec,0x3f3fc767,0xbf299415,0x3eee9479,0xbf628210,0x3e7ab273,0xbffe1324,0xbe72b651,0xbf78b47b,0xbf10d3cd,0xbf531849,0xbf5233c6,0xbf121eb0,
0x3f800000,0x0,0x3f6e46be,0xbebb31a0,0x3f3b8f3b,0xbf2e3bde,0x3eddbe79,0xbf66becc,0x3e16a905,0xbfff4e6d,0xbe97a117,0xbf748422,0xbf1ff6cb,0xbf47de65,0xbf5df6be,0xbeff17b2,
0x3f800000,0x0,0x3f6d1c1d,0xbec1071e,0x3f373a23,0xbf32c8c9,0x3ecc9b8b,0xbf6aab7b,0x3d490ab0,0xbfffec43,0xbeb554ec,0xbf6f6830,0xbf2e3bde,0xbf3b8f3b,0xbf6816a8,0xbed8106b,
0x3f800000,0x0,0x3f7ffd39,0xbc16cb58,0x3f7ff4e6,0xbc96c9b6,0x3f7fe705,0xbce22a7a,0x3fffd397,0xbd96c32c,0x3f7fba9e,0xbd3c6dd5,0x3f7f9c18,0xbd621469,0x3f7f7808,0xbd83db0a,
0x3f800000,0x0,0x3f7ff0e3,0xbcafea69,0x3f7fc38f,0xbd2fe007,0x3f7f7808,0xbd83db0a,0x3fff0e58,0xbe2fb680,0x3f7e868b,0xbddb7d37,0x3f7de0b1,0xbe039502,0x3f7d1cdd,0xbe195be0,
0x3f800000,0x0,0x3f7fdaaf,0xbd0a342f,0x3f7f6ac7,0xbd8a200a,0x3f7eb069,0xbdcefdb7,0x3ffdabcc,0xbe89cf86,0x3f7c5d3a,0xbe2bf804,0x3f7ac516,0xbe4dee60,0x3f78e3d6,0xbe6fa8b2,
0x3f800000,0x0,0x3f7fba9e,0xbd3c6dd5,0x3f7eea9d,0xbdbc3ac3,0x3f7d906e,0xbe0cec4a,0x3ffbaccd,0xbebb6ecf,0x3f7940c0,0xbe698bba,0x3f764d97,0xbe8b9507,0x3f72d4eb,0xbea21887,
0x3f800000,0x0,0x3f7f90b1,0xbd6ea038,0x3f7e4323,0xbdee3876,0x3f7c187a,0xbe3228d4,0x3ff91298,0xbeec9a7f,0x3f75341d,0xbe931f35,0x3f708066,0xbeaf713a,0x3f6afb8c,0xbecb2aae,
0x3f800000,0x0,0x3f7f5ce9,0xbd9064b4,0x3f7d7474,0xbe1008b7,0x3f7a4910,0xbe57278f,0x3ff5dec6,0xbf0e9a22,0x3f703b37,0xbeb0eacb,0x3f696591,0xbed25a09,0x3f61668a,0xbef2bd43,
0x3f800000,0x0,0x3f7f1f49,0xbda973ba,0x3f7c7eb0,0xbe28defc,0x3f7822d1,0xbe7bdba4,0x3ff21352,0xbf268f12,0x3f6a5ad9,0xbece0bea,0x3f6106f2,0xbef41f07,0x3f5627fe,0xbf0c42c9,
0x3f800000,0x0,0x3f7ed7d4,0xbdc27c39,0x3f7b61fc,0xbe419b37,0x3f75a67b,0xbe901c2c,0x3fedb293,0xbf3e1d4a,0x3f6398ac,0xbeea6681,0x3f577026,0xbf0a48ad,0x3f495521,0xbf1e1e22,
0x3f800000,0x0,0x3f7e868b,0xbddb7d37,0x3f7a1e84,0xbe5a3997,0x3f72d4eb,0xbea21887,0x3fe8bf3c,0xbf553641,0x3f5bfb34,0xbf02ef9f,0x3f4cae79,0xbf19c200,0x3f3b0629,0xbf2ecef7,
0x3f800000,0x0,0x3f7e2b72,0xbdf475c0,0x3f78b47b,0xbe72b651,0x3f6faf1b,0xbeb3dca5,0x3fe33c5a,0xbf6bcbbb,0x3f5389c7,0xbf102dd5,0x3f40d0da,0xbf286605,0x3f2b561b,0xbf3e35c5,
0x3f800000,0x0,0x3f7dc68c,0xbe06b26e,0x3f772417,0xbe8586ce,0x3f6c3624,0xbec5625c,0x3fdd2d53,0xbf80e7e4,0x3f4a4c87,0xbf1ce11f,0x3f33e7bc,0xbf36206c,0x3f1a6293,0xbf4c3578,
0x3f800000,0x0,0x3f7d57de,0xbe1324ca,0x3f756d97,0xbe919ddd,0x3f686b39,0xbed6a399,0x3fd695e5,0xbf8b9a6b,0x3f404c5c,0xbf28fd41,0x3f26050a,0xbf42de29,0x3f084b92,0xbf58b3a1,
0x3f800000,0x0,0x3f7cdf6c,0xbe1f917b,0x3f73913f,0xbe9d9e78,0x3f644fac,0xbee79a5d,0x3fcf7a1f,0xbf95f6d9,0x3f3592e7,0xbf34768f,0x3f173c07,0xbf4e8d90,0x3eea6681,0xbf6398ac,
0x3f800000,0x0,0x3f7c5d3a,0xbe2bf804,0x3f718f57,0xbea986c4,0x3f5fe4e9,0xbef840c8,0x3fc7de65,0xbf9ff6cb,0x3f2a2a80,0xbf3f41fc,0x3f07a136,0xbf591e6a,0x3ec27b55,0xbf6cd007,
0x3f800000,0x0,0x3f7bd14d,0xbe3857ec,0x3f6f6830,0xbeb554ec,0x3f5b2c79,0xbf044889,0x3fbfc767,0xbfa99415,0x3f1e1e22,0xbf495521,0x3eee9479,0xbf628210,0x3e9920fe,0xbf74484b,
0x3f800000,0x0,0x3f7b3bab,0xbe44b0b9,0x3f6d1c1d,0xbec1071e,0x3f5627fe,0xbf0c42c9,0x3fb73a23,0xbfb2c8c9,0x3f11796b,0xbf52a649,0x3ecc9b8b,0xbf6aab7b,0x3e5d4b1a,0xbf79f35e,
0x3f800000,0x0,0x3f7a9c59,0xbe5101f1,0x3f6aab7b,0xbecc9b8b,0x3f50d937,0xbf140c5f,0x3fae3bde,0xbfbb8f3b,0x3f044889,0xbf5b2c79,0x3ea986c4,0xbf718f57,0x3e06b26e,0xbf7dc68c,
0x3f800000,0x0,0x3f79f35e,0xbe5d4b1a,0x3f6816a8,0xbed8106b,0x3f4b41fa,0xbf1ba299,0x3fa4d225,0xbfc3e200,0x3eed3063,0xbf62df7b,0x3e8586ce,0xbf772417,0x3d3c6dd5,0xbf7fba9e,
0x3f800000,0x0,0x3f7940c0,0xbe698bba,0x3f655e0b,0xbee363fa,0x3f456439,0xbf2302d3,0x3f9b02c6,0xbfcbbbf8,0x3ed0eb2a,0xbf69b7e4,0x3e419b37,0xbf7b61fc,0xbd2351cb,0xbf7fcbe2,
0x3f800000,0x0,0x3f788486,0xbe75c35a,0x3f628210,0xbeee9479,0x3f3f41fc,0xbf2a2a80,0x3f90d3cd,0xbfd31849,0x3eb3dca5,0xbf6faf1b,0x3dee3876,0xbf7e4323,0xbe007745,0xbf7dfa38,
0x3f800000,0x0,0x3f77beb7,0xbe80f8c0,0x3f5f8327,0xbef9a02d,0x3f38dd65,0xbf311722,0x3f864b82,0xbfd9f26a,0x3e9620d2,0xbf74bf62,0x3d2fe007,0xbf7fc38f,0xbe57278f,0xbf7a4910,
0x3f800000,0x0,0x3f76ef5b,0xbe870ada,0x3f5c61c7,0xbf0242b1,0x3f3238aa,0xbf37c655,0x3f76e0cb,0xbfe04621,0x3e6fa8b2,0xbf78e3d6,0xbcfb49ba,0xbf7fe129,0xbe9620d2,0xbf74bf62,
0x3f800000,0x0,0x3f76167a,0xbe8d17c0,0x3f591e6a,0xbf07a136,0x3f2b561b,0xbf3e35c5,0x3f60924f,0xbfe60f88,0x3e3228d4,0xbf7c187a,0xbdd53db9,0xbf7e9bc9,0xbebf926f,0xbf6d67a1,
0x3f800000,0x0,0x3f75341d,0xbe931f35,0x3f55b993,0xbf0cead0,0x3f24381a,0xbf446337,0x3f49b953,0xbfeb4b0c,0x3de7fa9a,0xbf7e5a38,0xbe354098,0xbf7bf531,0xbee79a5d,0xbf644fac,
0x3f800000,0x0,0x3f74484b,0xbe9920fe,0x3f5233c6,0xbf121eb0,0x3f1ce11f,0xbf4a4c87,0x3f3263ef,0xbfeff573,0x3d55880e,0xbf7fa6e3,0xbe7ee6e1,0xbf77f110,0xbf06f686,0xbf5988ad,
0x3f800000,0x0,0x3f73530e,0xbe9f1cdf,0x3f4e8d90,0xbf173c07,0x3f1553b7,0xbf4fefa8,0x3f1aa086,0xbff40bdd,0xbc16cb58,0xbf7ffd39,0xbea395c5,0xbf7294f8,0xbf19210f,0xbf4d26fd,
0x3f800000,0x0,0x3f725470,0xbea5129f,0x3f4ac77f,0xbf1c420c,0x3f0d9281,0xbf554aa4,0x3f027dc0,0xbff78bc5,0xbd9064b4,0xbf7f5ce9,0xbec6d529,0xbf6be858,0xbf2a2a80,0xbf3f41fc,
0x3f800000,0x0,0x3f714c7a,0xbeab0201,0x3f46e22a,0xbf212ff9,0x3f05a02c,0xbf5a5ba0,0x3ed41501,0xbffa7302,0xbe06b26e,0xbf7dc68c,0xbee900b7,0xbf63f473,0xbf39f2ac,0xbf2ff3e6,
0x3f800000,0x0,0x3f703b37,0xbeb0eacb,0x3f42de29,0xbf26050a,0x3efafef7,0xbf5f20db,0x3ea2abb6,0xbffcbfc9,0xbe44b0b9,0xbf7b3bab,0xbf04f484,0xbf5ac450,0xbf485bca,0xbf1f599f,
0x3f800000,0x0,0x3f6f20b0,0xbeb6ccc3,0x3f3ebc1b,0xbf2ac082,0x3eea6681,0xbf6398ac,0x3e61bc2e,0xbffe70b0,0xbe80f8c0,0xbf77beb7,0xbf14b039,0xbf5064af,0xbf554aa4,0xbf0d9281,
0x3f800000,0x0,0x3f6dfcf2,0xbebca7af,0x3f3a7ca4,0xbf2f61a5,0x3ed97cb9,0xbf67c187,0x3dfb2b74,0xbfff84ab,0xbe9f1cdf,0xbf73530e,0xbf239da9,0xbf44e3f5,0xbf60a6cf,0xbef58035,
0x3f800000,0x0,0x3f6cd007,0xbec27b55,0x3f36206c,0xbf33e7bc,0x3ec8477c,0xbf6b99fb,0x3cc90e90,0xbffffb11,0xbebca7af,0xbf6dfcf2,0xbf31a81d,0xbf385216,0xbf6a5ad9,0xbece0bea,
0x3f800000,0x0,0x0,0x0,0x0,0x0,0x0,0x0,0x0,0x0,0x0,0x0,0x0,0x0,0x0,0x0,
0x0,0x0,0x0,0x0,0x0,0x0,0x0,0x0,0x0,0x0,0x0,0x0,0x0,0x0,0x0,0x0,
0x0,0x0,0x3e000000,0xbf20dff7,0x3ed0c429,0x0,0x3e000000,0x3e61f78b,0x3e0a8bd4,0x0,0x3e000000,0x3d5413cd,0x3d5df9ad,0x0,0x3e000000,0x3cf043ab,
0x0,0x0,0x3e000000,0x3ccbafaf,0xbd5df9ad,0x0,0x3e000000,0x3cf043ab,0xbe0a8bd4,0x0,0x3e000000,0x3d5413cd,0xbed0c429,0x0,0x3e000000,0x3e61f78b,
0x0,0x0,0x0,0x0,0x3f000000,0x0,0x0,0x3f000000,0x0,0x0,0x0,0x0,0x0,0x0,0x0,0x0,
0x0,0x0,0x0,0x0,0x0,0x0,0x0,0x0,0x0,0x0,0x0,0x0,0x3f000000,0x0,0x0,0xbf000000,
0x0,0x0,0x3e000000,0xbe3f90c7,0xbe8b7e3f,0x0,0x3e000000,0xbeb641af,0x3ea73d75,0x0,0x3e000000,0x3e9a827a,0x3da61ad1,0x0,0x3e000000,0x3dd906bd,
0x0,0x0,0x3e000000,0x3dab0dc1,0xbda61ad1,0x0,0x3e000000,0x3dd906bd,0xbea73d75,0x0,0x3e000000,0x3e9a827a,0x3e8b7e3f,0x0,0x3e000000,0xbeb641af,
0x0,0x0,0x0,0x0,0x0,0x0,0x0,0x0,0x3f000000,0x0,0x0,0x3f000000,0x0,0x0,0x0,0x0,
0x0,0x0,0x0,0x0,0x0,0x0,0x0,0x0,0x3f000000,0x0,0x0,0xbf000000,0x0,0x0,0x0,0x0,
0x0,0x0,0x3e000000,0xbdab0dc1,0xbda61ad1,0x0,0x3e000000,0xbdd906bd,0xbea73d75,0x0,0x3e000000,0xbe9a827a,0x3e8b7e3f,0x0,0x3e000000,0x3eb641af,
0x0,0x0,0x3e000000,0x3e3f90c7,0xbe8b7e3f,0x0,0x3e000000,0x3eb641af,0x3ea73d75,0x0,0x3e000000,0xbe9a827a,0x3da61ad1,0x0,0x3e000000,0xbdd906bd,
0x0,0x0,0x0,0x0,0x0,0x0,0x0,0x0,0x0,0x0,0x0,0x0,0x3f000000,0x0,0x0,0x3f000000,
0x0,0x0,0x0,0x0,0x3f000000,0x0,0x0,0xbf000000,0x0,0x0,0x0,0x0,0x0,0x0,0x0,0x0,
0x0,0x0,0x3e000000,0xbccbafaf,0xbd5df9ad,0x0,0x3e000000,0xbcf043ab,0xbe0a8bd4,0x0,0x3e000000,0xbd5413cd,0xbed0c429,0x0,0x3e000000,0xbe61f78b,
0x0,0x0,0x3e000000,0x3f20dff7,0x3ed0c429,0x0,0x3e000000,0xbe61f78b,0x3e0a8bd4,0x0,0x3e000000,0xbd5413cd,0x3d5df9ad,0x0,0x3e000000,0xbcf043ab,
};

struct Params {
    const __nv_bfloat16 *wr, *wi, *lre, *lim, *ldt, *dsk;
    float* out;
};

struct cf { float x, y; };
#define YIELD() asm volatile("pmevent 1;")
#define YS 14
#define YIELD_S1() do { if (YS & 1) YIELD(); } while (0)
#define YIELD_S2() do { if (YS & 2) YIELD(); } while (0)
#define YIELD_S3() do { if (YS & 4) YIELD(); } while (0)
__device__ __forceinline__ uint32_t smem_u32(const void* p) { return (uint32_t)__cvta_generic_to_shared(p); }
__device__ __forceinline__ void mbar_init(uint32_t a, uint32_t c) { asm volatile("mbarrier.init.shared::cta.b64 [%0], %1;" ::"r"(a), "r"(c) : "memory"); }
__device__ __forceinline__ void mbar_expect_tx(uint32_t a, uint32_t b) { asm volatile("mbarrier.arrive.expect_tx.shared::cta.b64 _, [%0], %1;" ::"r"(a), "r"(b) : "memory"); }
__device__ __forceinline__ void mbar_arrive(uint32_t a) { asm volatile("mbarrier.arrive.shared::cta.b64 _, [%0];" ::"r"(a) : "memory"); }
__device__ __forceinline__ void warp_arrive(uint32_t a) {
    __syncwarp();
    asm volatile("{.reg .pred p; elect.sync _|p, 0xffffffff; @p mbarrier.arrive.shared::cta.b64 _, [%0];}" ::"r"(a) : "memory");
}
__device__ __forceinline__ uint32_t mbar_try(uint32_t a, uint32_t ph) {
    uint32_t ok;
    asm volatile("{.reg .pred p; mbarrier.try_wait.parity.shared::cta.b64 p, [%1], %2; selp.u32 %0, 1, 0, p;}" : "=r"(ok) : "r"(a), "r"(ph) : "memory");
    return ok;
}
__device__ __forceinline__ void mbar_wait(uint32_t a, uint32_t ph) {
    uint32_t ok, n = 0;
    do { ok = mbar_try(a, ph); } while (!ok && ++n < SPIN_LIMIT);
}
__device__ __forceinline__ void mbar_wait_fast(uint32_t a, uint32_t ph) { if (!mbar_try(a, ph)) mbar_wait(a, ph); }
__device__ __forceinline__ unsigned ld_rlx(const unsigned* p) { unsigned v; asm volatile("ld.relaxed.gpu.global.u32 %0, [%1];" : "=r"(v) : "l"(p) : "memory"); return v; }
__device__ __forceinline__ void wait_cnt(const unsigned* p, unsigned target) {
    unsigned n = 0;
    while ((int)(ld_rlx(p) - target) < 0 && ++n < SPIN_LIMIT) __nanosleep(20);
}
__device__ __forceinline__ void red_hint(unsigned* p) { asm volatile("red.relaxed.gpu.global.add.u32 [%0], 1;" ::"l"(p) : "memory"); }
__device__ __forceinline__ void fence_async_sm() { asm volatile("fence.proxy.async.shared::cta;" ::: "memory"); }
#define bar_sync(id, n) asm volatile("bar.sync %0, %1;" ::"n"(id), "n"(n) : "memory")
#define bar_arrive(id, n) asm volatile("bar.arrive %0, %1;" ::"n"(id), "n"(n) : "memory")
__device__ __forceinline__ bool elect_one() {
    uint32_t r;
    asm volatile("{.reg .pred p; elect.sync _|p, 0xffffffff; selp.u32 %0, 1, 0, p;}" : "=r"(r));
    return r != 0;
}

__device__ __forceinline__ void tma2d(uint32_t dst, const CUtensorMap* m, int c0, int c1, uint32_t bar) {
    asm volatile("cp.async.bulk.tensor.2d.shared::cluster.global.mbarrier::complete_tx::bytes [%0], [%1, {%3,%4}], [%2];" ::"r"(dst), "l"(m), "r"(bar), "r"(c0), "r"(c1) : "memory");
}
__device__ __forceinline__ void tma3d(uint32_t dst, const CUtensorMap* m, int c0, int c1, int c2, uint32_t bar) {
    asm volatile("cp.async.bulk.tensor.3d.shared::cluster.global.mbarrier::complete_tx::bytes [%0], [%1, {%3,%4,%5}], [%2];" ::"r"(dst), "l"(m), "r"(bar), "r"(c0), "r"(c1), "r"(c2) : "memory");
}
__device__ __forceinline__ void tma4d_mc(uint32_t dst, const CUtensorMap* m, int c0, int c1, int c2, int c3, uint32_t bar) {
    asm volatile("cp.async.bulk.tensor.4d.shared::cluster.global.mbarrier::complete_tx::bytes.multicast::cluster [%0], [%1, {%3,%4,%5,%6}], [%2], %7;" ::"r"(dst), "l"(m), "r"(bar), "r"(c0), "r"(c1), "r"(c2), "r"(c3), "h"((uint16_t)3) : "memory");
}
__device__ __forceinline__ void tma4d(uint32_t dst, const CUtensorMap* m, int c0, int c1, int c2, int c3, uint32_t bar) {
    asm volatile("cp.async.bulk.tensor.4d.shared::cluster.global.mbarrier::complete_tx::bytes [%0], [%1, {%3,%4,%5,%6}], [%2];" ::"r"(dst), "l"(m), "r"(bar), "r"(c0), "r"(c1), "r"(c2), "r"(c3) : "memory");
}
__device__ __forceinline__ void tma2d_st(const CUtensorMap* m, int c0, int c1, uint32_t src) {
    asm volatile("cp.async.bulk.tensor.2d.global.shared::cta.bulk_group [%0, {%2,%3}], [%1];" ::"l"(m), "r"(src), "r"(c0), "r"(c1) : "memory");
}
__device__ __forceinline__ void tma5d(uint32_t dst, const CUtensorMap* m, int c0, int c1, int c2, int c3, int c4, uint32_t bar) {
    asm volatile("cp.async.bulk.tensor.5d.shared::cluster.global.mbarrier::complete_tx::bytes [%0], [%1, {%3,%4,%5,%6,%7}], [%2];" ::"r"(dst), "l"(m), "r"(bar), "r"(c0), "r"(c1), "r"(c2), "r"(c3), "r"(c4) : "memory");
}
__device__ __forceinline__ void bulk_ld(uint32_t dst, const void* src, uint32_t n, uint32_t bar) {
    asm volatile("cp.async.bulk.shared::cluster.global.mbarrier::complete_tx::bytes [%0], [%1], %2, [%3];" ::"r"(dst), "l"(src), "r"(n), "r"(bar) : "memory");
}
__device__ __forceinline__ void bulk_st(void* dst, uint32_t src, uint32_t n) {
    asm volatile("cp.async.bulk.global.shared::cta.bulk_group [%0], [%1], %2;" ::"l"(dst), "r"(src), "r"(n) : "memory");
}
__device__ __forceinline__ void bulk_commit() { asm volatile("cp.async.bulk.commit_group;" ::: "memory"); }
__device__ __forceinline__ void bulk_wait_read() { asm volatile("cp.async.bulk.wait_group.read 0;" ::: "memory"); }
__device__ __forceinline__ void bulk_wait_all() { asm volatile("cp.async.bulk.wait_group 0;" ::: "memory"); }
__device__ __forceinline__ void stsm4(uint32_t a, uint32_t r0, uint32_t r1, uint32_t r2, uint32_t r3) {
    asm volatile("stmatrix.sync.aligned.m8n8.x4.shared.b16 [%0], {%1,%2,%3,%4};" ::"r"(a), "r"(r0), "r"(r1), "r"(r2), "r"(r3) : "memory");
}
__device__ __forceinline__ void sts128(uint32_t a, uint32_t r0, uint32_t r1, uint32_t r2, uint32_t r3) {
    asm volatile("st.shared.v4.b32 [%0], {%1,%2,%3,%4};" ::"r"(a), "r"(r0), "r"(r1), "r"(r2), "r"(r3) : "memory");
}
__device__ __forceinline__ void lds128f(uint32_t a, float& x, float& y, float& z, float& u) { asm volatile("ld.shared.v4.f32 {%0,%1,%2,%3}, [%4];" : "=f"(x), "=f"(y), "=f"(z), "=f"(u) : "r"(a) : "memory"); }
__device__ __forceinline__ cf lds_cf(uint32_t a) { cf v; asm volatile("ld.shared.v2.f32 {%0,%1}, [%2];" : "=f"(v.x), "=f"(v.y) : "r"(a) : "memory"); return v; }
__device__ __forceinline__ void stg128(const void* a, uint32_t r0, uint32_t r1, uint32_t r2, uint32_t r3) {
    asm volatile("st.global.v4.b32 [%0], {%1,%2,%3,%4};" ::"l"(a), "r"(r0), "r"(r1), "r"(r2), "r"(r3) : "memory");
}
__device__ __forceinline__ int fresh_lane() { int v; asm volatile("mov.u32 %0, %%laneid;" : "=r"(v)); return v; }
__device__ __forceinline__ uint32_t opaque32(uint32_t v) { asm volatile("" : "+r"(v)); return v; }
__device__ __forceinline__ const uint8_t* padd(const void* base, uint32_t off) {
    uint64_t r;
    asm("{.reg .u32 l, h; mov.b64 {l, h}, %1; add.cc.u32 l, l, %2; addc.u32 h, h, 0; mov.b64 %0, {l, h};}" : "=l"(r) : "l"(base), "r"(off));
    return (const uint8_t*)r;
}
template <int N, int STRIDE> __device__ __forceinline__ void ldtab(uint32_t (&v)[4 * N], uint32_t off) {
    const uint8_t* a = padd(g_tab, off);
#pragma unroll
    for (int i = 0; i < N; i++)
        asm volatile("ld.global.nc.v4.b32 {%0,%1,%2,%3}, [%4];" : "=r"(v[4 * i]), "=r"(v[4 * i + 1]), "=r"(v[4 * i + 2]), "=r"(v[4 * i + 3]) : "l"(a + i * STRIDE));
}
template <int STRIDE> __device__ __forceinline__ void ldtab_cf(cf (&t)[8], uint32_t off) {
    uint32_t v[16];
    ldtab<4, STRIDE>(v, off);
#pragma unroll
    for (int i = 0; i < 8; i++) t[i] = {__uint_as_float(v[2 * i]), __uint_as_float(v[2 * i + 1])};
}
__device__ __forceinline__ uint32_t lds16(uint32_t a) { uint32_t v; asm volatile("ld.shared.u16 %0, [%1];" : "=r"(v) : "r"(a)); return v; }
__device__ __forceinline__ unsigned get_epoch(uint32_t bars) {
    mbar_wait(bars + B_EP, 0);
    unsigned e;
    asm volatile("ld.shared.u32 %0, [%1];" : "=r"(e) : "r"(bars + B_EPOCH) : "memory");
    return e;
}
__device__ __forceinline__ void sts64(uint32_t a, uint32_t x, uint32_t y) { asm volatile("st.shared.v2.b32 [%0], {%1,%2};" ::"r"(a), "r"(x), "r"(y) : "memory"); }
__device__ __forceinline__ uint32_t pk(float lo, float hi) { uint32_t r; asm("cvt.rn.bf16x2.f32 %0, %1, %2;" : "=r"(r) : "f"(hi), "f"(lo)); return r; }
__device__ __forceinline__ float bf2f(unsigned short v) { return __uint_as_float((uint32_t)v << 16); }

__device__ __forceinline__ uint64_t mkdesc(uint32_t addr, uint32_t lbo, uint32_t sbo, uint32_t swz) {
    return (uint64_t)((addr & 0x3FFFF) >> 4) | ((uint64_t)(lbo >> 4) << 16) | ((uint64_t)(sbo >> 4) << 32) | ((uint64_t)swz << 62);
}
__device__ __forceinline__ uint64_t opaque(uint64_t v) { asm volatile("" : "+l"(v)); return v; }
__device__ __forceinline__ void wg_fence() { asm volatile("wgmma.fence.sync.aligned;" ::: "memory"); }
__device__ __forceinline__ void wg_commit() { asm volatile("wgmma.commit_group.sync.aligned;" ::: "memory"); }
template <int N> __device__ __forceinline__ void wg_wait() { asm volatile("wgmma.wait_group.sync.aligned %0;" ::"n"(N) : "memory"); }
template <int N> __device__ __forceinline__ void pin(float (&d)[N]) {
#pragma unroll
    for (int i = 0; i < N; i++) asm volatile("" : "+f"(d[i])::"memory");
}
template <int N> __device__ __forceinline__ void pinu(uint32_t (&d)[N]) {
#pragma unroll
    for (int i = 0; i < N; i++) asm volatile("" : "+r"(d[i])::"memory");
}

#define R8(d, o) "+f"(d[o]), "+f"(d[o + 1]), "+f"(d[o + 2]), "+f"(d[o + 3]), "+f"(d[o + 4]), "+f"(d[o + 5]), "+f"(d[o + 6]), "+f"(d[o + 7])
#define L8 "%0,%1,%2,%3,%4,%5,%6,%7"
#define L32 L8 ",%8,%9,%10,%11,%12,%13,%14,%15,%16,%17,%18,%19,%20,%21,%22,%23,%24,%25,%26,%27,%28,%29,%30,%31"
#define L56 L32 ",%32,%33,%34,%35,%36,%37,%38,%39,%40,%41,%42,%43,%44,%45,%46,%47,%48,%49,%50,%51,%52,%53,%54,%55"
#define L64 L56 ",%56,%57,%58,%59,%60,%61,%62,%63"

template <int O, int TA, int TB, int N> __device__ __forceinline__ void mma128_ss(float (&d)[N], uint64_t da, uint64_t db, int sc) {
    asm volatile("{.reg .pred p; setp.ne.b32 p, %66, 0;\n"
                 "wgmma.mma_async.sync.aligned.m64n128k16.f32.bf16.bf16 {" L64 "}, %64, %65, p, 1, 1, %67, %68;}"
                 : R8(d, O), R8(d, O + 8), R8(d, O + 16), R8(d, O + 24), R8(d, O + 32), R8(d, O + 40), R8(d, O + 48), R8(d, O + 56)
                 : "l"(da), "l"(db), "r"(sc), "n"(TA), "n"(TB));
}
template <int O, int TB> __device__ __forceinline__ void mma128_rs(float (&d)[128], uint32_t a0, uint32_t a1, uint32_t a2, uint32_t a3, uint64_t db, int sc) {
    asm volatile("{.reg .pred p; setp.ne.b32 p, %69, 0;\n"
                 "wgmma.mma_async.sync.aligned.m64n128k16.f32.bf16.bf16 {" L64 "}, {%64,%65,%66,%67}, %68, p, 1, 1, %70;}"
                 : R8(d, O), R8(d, O + 8), R8(d, O + 16), R8(d, O + 24), R8(d, O + 32), R8(d, O + 40), R8(d, O + 48), R8(d, O + 56)
                 : "r"(a0), "r"(a1), "r"(a2), "r"(a3), "l"(db), "r"(sc), "n"(TB));
}
template <int TB> __device__ __forceinline__ void mma64_rs(float (&d)[32], uint32_t a0, uint32_t a1, uint32_t a2, uint32_t a3, uint64_t db, int sc) {
    asm volatile("{.reg .pred p; setp.ne.b32 p, %37, 0;\n"
                 "wgmma.mma_async.sync.aligned.m64n64k16.f32.bf16.bf16 {" L32 "}, {%32,%33,%34,%35}, %36, p, 1, 1, %38;}"
                 : R8(d, 0), R8(d, 8), R8(d, 16), R8(d, 24)
                 : "r"(a0), "r"(a1), "r"(a2), "r"(a3), "l"(db), "r"(sc), "n"(TB));
}
__device__ __forceinline__ void mma112_ss(float (&d)[64], uint64_t da, uint64_t db, int sc) {
    asm volatile("{.reg .pred p; setp.ne.b32 p, %58, 0;\n"
                 "wgmma.mma_async.sync.aligned.m64n112k16.f32.bf16.bf16 {" L56 "}, %56, %57, p, 1, 1, 0, 1;}"
                 : R8(d, 8), R8(d, 16), R8(d, 24), R8(d, 32), R8(d, 40), R8(d, 48), R8(d, 56)
                 : "l"(da), "l"(db), "r"(sc));
}
__device__ __forceinline__ void mma16_rs(float (&d)[64], uint32_t a0, uint32_t a1, uint32_t a2, uint32_t a3, uint64_t db, int sc) {
    asm volatile("{.reg .pred p; setp.ne.b32 p, %13, 0;\n"
                 "wgmma.mma_async.sync.aligned.m64n16k16.f32.bf16.bf16 {" L8 "}, {%8,%9,%10,%11}, %12, p, 1, 1, 1;}"
                 : R8(d, 0)
                 : "r"(a0), "r"(a1), "r"(a2), "r"(a3), "l"(db), "r"(sc));
}

__device__ __forceinline__ cf cmul(cf a, cf b) { return {fmaf(a.x, b.x, -a.y * b.y), fmaf(a.x, b.y, a.y * b.x)}; }
__device__ __forceinline__ cf cmulc(cf a, cf b) { return {fmaf(a.x, b.x, a.y * b.y), fmaf(a.y, b.x, -a.x * b.y)}; }
__device__ __forceinline__ cf cfma(cf a, cf b, cf c) { return {fmaf(a.x, b.x, fmaf(-a.y, b.y, c.x)), fmaf(a.x, b.y, fmaf(a.y, b.x, c.y))}; }
__device__ __forceinline__ cf csq(cf a) { return {fmaf(a.x, a.x, -a.y * a.y), (a.x * a.y) * 2.f}; }
__device__ __forceinline__ cf csel(int c, cf a, cf b) {
    cf r;
    asm("{.reg .pred p; setp.ne.s32 p, %2, 0; selp.f32 %0, %3, %5, p; selp.f32 %1, %4, %6, p;}" : "=f"(r.x), "=f"(r.y) : "r"(c), "f"(a.x), "f"(a.y), "f"(b.x), "f"(b.y));
    return r;
}
__device__ __forceinline__ cf cadd(cf a, cf b) { return {a.x + b.x, a.y + b.y}; }
__device__ __forceinline__ cf csub(cf a, cf b) { return {a.x - b.x, a.y - b.y}; }
__device__ __forceinline__ cf twice_minus(cf a, cf s) { return {fmaf(2.f, a.x, -s.x), fmaf(2.f, a.y, -s.y)}; }
__device__ __forceinline__ cf twid(int m, int M) {
    int r = ((m + M / 2) & (M - 1)) - M / 2;
    float s, c;
    __sincosf((float)r * (-6.283185307179586f / (float)M), &s, &c);
    return {c, s};
}
struct c2 { cf a, b; };
#define YP1 3
#define YP3 3
template <int Y> __device__ __forceinline__ void fin(c2& u) { if (Y & 1) asm volatile("pmevent 1;" : "+f"(u.a.x), "+f"(u.a.y), "+f"(u.b.x), "+f"(u.b.y)); }
template <int Y> __device__ __forceinline__ void fin(c2& u, c2& v) {
    if (Y & 2) asm volatile("pmevent 1;" : "+f"(u.a.x), "+f"(u.a.y), "+f"(u.b.x), "+f"(u.b.y), "+f"(v.a.x), "+f"(v.a.y), "+f"(v.b.x), "+f"(v.b.y));
}
__device__ __forceinline__ c2 mul2(c2 u, cf t) { return {cmul(u.a, t), cmul(u.b, t)}; }
__device__ __forceinline__ c2 mul2(c2 u, c2 t) { return {cmul(u.a, t.a), cmul(u.b, t.b)}; }
__device__ __forceinline__ c2 fma2(c2 u, cf t, c2 c) { return {cfma(u.a, t, c.a), cfma(u.b, t, c.b)}; }
__device__ __forceinline__ c2 fma2(c2 u, c2 t, c2 c) { return {cfma(u.a, t.a, c.a), cfma(u.b, t.b, c.b)}; }
__device__ __forceinline__ c2 twm2(c2 u, c2 s) { return {twice_minus(u.a, s.a), twice_minus(u.b, s.b)}; }
template <int Y> __device__ __forceinline__ void bfly(c2& u, c2& v) { const c2 t = u; u = {cadd(t.a, v.a), cadd(t.b, v.b)}; v = {csub(t.a, v.a), csub(t.b, v.b)}; fin<Y>(u, v); }
template <int Y> __device__ __forceinline__ void bfly_mi(c2& u, c2& v) {
    const c2 t = u, z = v;
    u = {{t.a.x + z.a.y, t.a.y - z.a.x}, {t.b.x + z.b.y, t.b.y - z.b.x}};
    v = {{t.a.x - z.a.y, t.a.y + z.a.x}, {t.b.x - z.b.y, t.b.y + z.b.x}};
    fin<Y>(u, v);
}
template <int Y> __device__ __forceinline__ void bfly_s(c2& u, c2& v) {
    const float s = 0.70710678118654752f;
    const c2 t = u, z = v;
    u = {{fmaf(s, z.a.x, t.a.x), fmaf(s, z.a.y, t.a.y)}, {fmaf(s, z.b.x, t.b.x), fmaf(s, z.b.y, t.b.y)}};
    v = {{fmaf(-s, z.a.x, t.a.x), fmaf(-s, z.a.y, t.a.y)}, {fmaf(-s, z.b.x, t.b.x), fmaf(-s, z.b.y, t.b.y)}};
    fin<Y>(u, v);
}
template <int Y, class T> __device__ __forceinline__ void bfly_tw(c2& u0, c2& v0, T t0, c2& u1, c2& v1, T t1) {
    v0 = fma2(v0, t0, u0); fin<Y>(v0);
    v1 = fma2(v1, t1, u1); fin<Y>(v1);
    const c2 a = twm2(u0, v0), b = twm2(u1, v1);
    u0 = v0; u1 = v1; v0 = a; v1 = b;
    fin<Y>(v0, v1);
}
template <bool TW, int Y> __device__ __forceinline__ void dft8(c2 (&v)[8], const cf (&tw)[8]) {
    if (TW) {
#pragma unroll
        for (int n = 1; n < 4; n++) { v[n] = mul2(v[n], tw[n]); fin<Y>(v[n]); }
        bfly_tw<Y>(v[0], v[4], tw[4], v[2], v[6], tw[6]);
        bfly_tw<Y>(v[1], v[5], tw[5], v[3], v[7], tw[7]);
    } else {
#pragma unroll
        for (int n = 0; n < 4; n++) bfly<Y>(v[n], v[n + 4]);
    }
    bfly<Y>(v[0], v[2]); bfly_mi<Y>(v[4], v[6]);
    bfly<Y>(v[1], v[3]); bfly_mi<Y>(v[5], v[7]);
    v[5] = {{v[5].a.x + v[5].a.y, v[5].a.y - v[5].a.x}, {v[5].b.x + v[5].b.y, v[5].b.y - v[5].b.x}};
    v[7] = {{v[7].a.y - v[7].a.x, -v[7].a.x - v[7].a.y}, {v[7].b.y - v[7].b.x, -v[7].b.x - v[7].b.y}};
    fin<Y>(v[5], v[7]);
    bfly<Y>(v[0], v[1]); bfly_s<Y>(v[4], v[5]); bfly_mi<Y>(v[2], v[3]); bfly_s<Y>(v[6], v[7]);
    const c2 t1 = v[1], t3 = v[3];
    v[1] = v[4]; v[4] = t1; v[3] = v[6]; v[6] = t3;
}

__device__ __forceinline__ void gather(uint64_t (&fv)[4], const uint8_t* a, int n) {
    asm volatile("{.reg .pred p0, p1, p2, p3;\n"
                 "setp.ge.s32 p0, %5, 0; setp.ge.s32 p1, %5, 4; setp.ge.s32 p2, %5, 8; setp.ge.s32 p3, %5, 12;\n"
                 "@p0 ld.relaxed.gpu.global.b64 %0, [%4]; @p1 ld.relaxed.gpu.global.b64 %1, [%4+-32768];\n"
                 "@p2 ld.relaxed.gpu.global.b64 %2, [%4+-65536]; @p3 ld.relaxed.gpu.global.b64 %3, [%4+-98304];}"
                 : "+l"(fv[0]), "+l"(fv[1]), "+l"(fv[2]), "+l"(fv[3]) : "l"(a), "r"(n) : "memory");
}
__device__ __forceinline__ cf as_cf(uint64_t v) { cf r; asm("mov.b64 {%0,%1}, %2;" : "=f"(r.x), "=f"(r.y) : "l"(v)); return r; }
template <int H> __device__ __forceinline__ void prescale(float (&u)[64], const float (&d)[128], cf gam) {
#pragma unroll
    for (int i = 0; i < 32; i += 2) {
        const int r = 2 * i + 2 * H;
        c2 v = mul2(c2{{d[r], -d[64 + r]}, {d[r + 1], -d[65 + r]}}, gam);
        if (YS & 2) asm volatile("pmevent 1;" : "+f"(v.a.x), "+f"(v.a.y), "+f"(v.b.x), "+f"(v.b.y));
        u[i] = v.a.x; u[32 + i] = v.a.y; u[i + 1] = v.b.x; u[33 + i] = v.b.y;
    }
}
__device__ __forceinline__ void scan2(const float (&u)[64], cf lam, cf st, const uint8_t* hptr, uint32_t hm, uint32_t hb, uint32_t& keep) {
    uint32_t hp[32];
#pragma unroll
    for (int jj = 0; jj < 4; jj++) {
        cf v[8];
#pragma unroll
        for (int i = 0; i < 8; i++) v[i] = st = cfma(lam, st, {u[8 * jj + i], u[32 + 8 * jj + i]});
        const int o = 8 * jj;
        hp[o] = pk(v[0].x, v[2].x); hp[o + 1] = pk(v[4].x, v[6].x); hp[o + 2] = pk(v[1].x, v[3].x); hp[o + 3] = pk(v[5].x, v[7].x);
        hp[o + 4] = pk(v[0].y, v[2].y); hp[o + 5] = pk(v[4].y, v[6].y); hp[o + 6] = pk(v[1].y, v[3].y); hp[o + 7] = pk(v[5].y, v[7].y);
        hp[o + jj] = (hp[o + jj] & hm) | hb;
        hp[o + 4 + jj] = (hp[o + 4 + jj] & hm) | hb;
        stg128(hptr + (jj >> 1) * 8192 + (jj & 1) * 512, hp[o], hp[o + 1], hp[o + 2], hp[o + 3]);
        stg128(hptr + 16384 + (jj >> 1) * 8192 + (jj & 1) * 512, hp[o + 4], hp[o + 5], hp[o + 6], hp[o + 7]);
        YIELD_S3();
        if (jj > 0) {
#pragma unroll
            for (int i = o - 8; i < o; i += 2) asm volatile("lop3.b32 %0, %0, %1, %2, 0x80;" : "+r"(keep) : "r"(hp[i]), "r"(hp[i + 1]));
        }
    }
}

__device__ __forceinline__ int pos_of(int n) { return (n & 24) + 4 * (n & 1) + ((n >> 1) & 3); }
__device__ __forceinline__ int unit_of(int role, int u, int& slot) {
    const int g = role & 7, w = (role >> 3) & 3, b = role >> 5;
    slot = role >= 128 ? g : (g ? 16 * g + w + 4 * b : 4 * w + b);
    return role >= 128 ? 32 * max(2 * g + u, 1) : (g ? g + 16 * w : ((w & 1) << 4) + ((w & 2) << 2)) + 64 * b + 256 * u;
}
template <int STRIDE> __device__ __forceinline__ bool tags_ok(uint32_t a, uint32_t ep) {
    uint32_t v[4], ok;
#pragma unroll
    for (int i = 0; i < 4; i++) asm volatile("ld.shared.u32 %0, [%1];" : "=r"(v[i]) : "r"(a + i * STRIDE) : "memory");
    asm volatile("{.reg .pred p; .reg .b32 a, b; lop3.b32 a, %1, %2, %5, 0x7e; lop3.b32 b, %3, %4, %5, 0x7e; lop3.b32 a, a, b, 1, 0xa8;\n"
                 "setp.eq.u32 p, a, 0; vote.sync.all.pred p, p, -1; selp.u32 %0, 1, 0, p;}" : "=r"(ok) : "r"(v[0]), "r"(v[1]), "r"(v[2]), "r"(v[3]), "r"(ep));
    return ok;
}
__device__ __forceinline__ void load_w_rows(uint32_t dst, const CUtensorMap* mr, const CUtensorMap* mi, int kap, uint32_t bar) {
    mbar_expect_tx(bar, 16 * WPITCH);
#pragma unroll 1
    for (int i = 0; i < 2; i++, dst += 8 * WPITCH, kap = (512 - kap) & 511) {
        tma2d(dst, mr, (kap * 1026 >> 4) * 2, 0, bar);
        tma2d(dst + 4 * WPITCH, mi, (kap * 1026 >> 4) * 2, 0, bar);
    }
}
__device__ __forceinline__ void prefetch_w_rows(const CUtensorMap* mr, const CUtensorMap* mi, int kap) {
#pragma unroll 1
    for (int i = 0; i < 2; i++, kap = (512 - kap) & 511) {
        asm volatile("cp.async.bulk.prefetch.tensor.2d.L2.global [%0, {%1,%2}];" ::"l"(mr), "r"((kap * 1026 >> 4) * 2), "r"(0) : "memory");
        asm volatile("cp.async.bulk.prefetch.tensor.2d.L2.global [%0, {%1,%2}];" ::"l"(mi), "r"((kap * 1026 >> 4) * 2), "r"(0) : "memory");
    }
}
template <int K0, int K1> __device__ __forceinline__ void store_v(const uint32_t (&vo)[32], const uint8_t* vp, bool p) {
    if (p) {
#pragma unroll
        for (int k = K0; k < K1; k++)
            asm volatile("st.global.v2.b32 [%0], {%1,%2};" ::"l"(vp + (k >> 2) * (1 << 20) + ((k >> 1) & 1) * 8192 + (k & 1) * (4 * 32768)), "r"(vo[2 * k]), "r"(vo[2 * k + 1]) : "memory");
    }
}
#define SB0 1024
__device__ __forceinline__ uint64_t ring_desc(uint32_t sb, uint32_t off, uint32_t lbo, uint32_t swz) {
    uint64_t d;
    asm volatile("{.reg .b32 z; shr.u32 z, %1, 28; mov.b64 %0, {z, z}; add.u64 %0, %0, %2;}" : "=l"(d) : "r"(sb), "l"(mkdesc(SB0 + off, lbo, 1024, swz)));
    return d;
}
struct Ring {
    uint32_t full, rel;
    uint32_t n;
    bool sig;
};
__device__ __forceinline__ void ring_release(const Ring& r, uint32_t o) {
    if (r.sig) asm volatile("mbarrier.arrive.shared::cluster.b64 _, [%0];" ::"r"(r.rel + o) : "memory");
}
__device__ __forceinline__ void peek(uint32_t a, uint32_t ph) { asm volatile("mbarrier.test_wait.parity.shared::cta.b64 pk, [%0], %1;" ::"r"(a), "r"(ph) : "memory"); }
__device__ __forceinline__ void peek_wait(uint32_t a, uint32_t ph, uint32_t& n) {
    asm volatile("{@pk bra DONE;\n"
                 "LOOP: mbarrier.try_wait.parity.shared::cta.b64 pk, [%1], %2; add.u32 %0, %0, 1; setp.gt.or.u32 pk, %0, %3, pk; @!pk bra LOOP;\n"
                 "DONE: }" : "+r"(n) : "r"(a), "r"(ph), "n"(SPIN_LIMIT) : "memory");
}
#define SL(k) ((k) % NST)
#define PH(k) (((k) / NST) & 1)
#define H64 "%64,%65,%66,%67,%68,%69,%70,%71,%72,%73,%74,%75,%76,%77,%78,%79,%80,%81,%82,%83,%84,%85,%86,%87,%88,%89,%90,%91,%92,%93,%94,%95," \
            "%96,%97,%98,%99,%100,%101,%102,%103,%104,%105,%106,%107,%108,%109,%110,%111,%112,%113,%114,%115,%116,%117,%118,%119,%120,%121,%122,%123,%124,%125,%126,%127"
#define WG_MMA "wgmma.mma_async.sync.aligned.m64n128k16.f32.bf16.bf16 "
#define DESC_B(S, j) "mov.b64 {t, hb}, %130; mov.b64 db, {%137 + 2048 * " #S " + 2 * " #j ", hb};\n"
#define MMA_LO(S, j, p) "add.u64 da, %129, 2048 * " #S " + %136 * " #j ";" DESC_B(S, j) WG_MMA "{" L64 "}, da, db, " #p ", 1, 1, %138, 0;\n"
#define MMA_HI(S, j, p) "add.u64 da, %129, 2048 * " #S " + 512 + %136 * " #j ";\n" WG_MMA "{" H64 "}, da, db, " #p ", 1, 1, %138, 0;\n"
#define STEP(S, P, N, ph, pa, pr, X, Y) \
    "wgmma.fence.sync.aligned;\n" MMA_LO(S, 0, pa) MMA_HI(S, 0, pa) \
    "wgmma.commit_group.sync.aligned; wgmma.wait_group.sync.aligned 1; @" #pr " mbarrier.arrive.shared::cluster.b64 _, [%132 + 8 * " #P "];\n" MMA_LO(S, 1, 1) \
    "mbarrier.test_wait.parity.shared::cta.b64 pk, [%131 + 8 * " #N "], " #ph ";\n" MMA_HI(S, 1, 1) MMA_LO(S, 2, 1) X MMA_HI(S, 2, 1) MMA_LO(S, 3, 1) MMA_HI(S, 3, 1) \
    "wgmma.commit_group.sync.aligned;\n" P4A Y "@pk bra GO" #S ";\n" \
    "WAIT" #S ": mbarrier.try_wait.parity.shared::cta.b64 pk, [%131 + 8 * " #N "], " #ph "; add.u32 %128, %128, 1; setp.gt.or.u32 pk, %128, %139, pk; @!pk bra WAIT" #S ";\n" \
    "GO" #S ":\n" P4B
#define P4A
#define P4B
#define P4I
#define P4O
#define STEP_ARGS(TA) \
    : R8(d, 0), R8(d, 8), R8(d, 16), R8(d, 24), R8(d, 32), R8(d, 40), R8(d, 48), R8(d, 56), \
      R8(d, 64), R8(d, 72), R8(d, 80), R8(d, 88), R8(d, 96), R8(d, 104), R8(d, 112), R8(d, 120), "+r"(r.n) \
    : "l"(ha), "l"(hb), "r"(r.full), "r"(r.rel), "r"((uint32_t)r.sig), "r"(wg), \
      "n"(SB0 / 16 + (TA ? 32 << 16 : 1 << 16)), "n"(TA ? 128 : 2), "n"(SB0 / 16 + 1024 + (1 << 16)), "n"(TA), "n"(SPIN_LIMIT) P4O \
    : "memory"
#define STEP_REGS "{.reg .b32 k, t, ph, hb; .reg .b64 da, db; .reg .pred ps, pl, pa, pr;\n" P4I "setp.ne.u32 ps, %133, 0;\n"
#define FIRST_WAIT "FIRST: mbarrier.try_wait.parity.shared::cta.b64 pk, [t], ph; @pk bra START; add.u32 %128, %128, 1; setp.le.u32 pk, %128, %139; @pk bra FIRST; START:\n"
__device__ __forceinline__ void gemm1(float (&d)[128], Ring& r, uint64_t ha, uint64_t hb, int wg) {
    asm volatile(STEP_REGS "mul.lo.u32 k, %134, 15; mov.b32 ph, %134; setp.ne.u32 pl, k, 0; mad.lo.u32 t, %134, 8, %131;\n"
                 "pmevent 1; @pl bar.sync 1, 256;\n" FIRST_WAIT "@pl bra ONE;\n"
                 "LOOP: setp.ne.u32 pa, k, 0; and.pred pr, pa, ps; setp.eq.u32 pl, k, 15;\n"
                 STEP(0, 4, 1, ph, pa, pr, "@pl bar.arrive 1, 256;\n", "@pl bra END;\n")
                 "ONE: setp.ne.u32 pa, k, 15; and.pred pr, pa, ps; setp.eq.u32 pl, k, 30;\n"
                 STEP(1, 0, 2, ph, pa, pr, "@pl bar.arrive 2, 256;\n", "@pl bra END;\n")
                 STEP(2, 1, 3, ph, 1, ps, "", "") STEP(3, 2, 4, ph, 1, ps, "", "") "xor.b32 ph, ph, 1; add.u32 k, k, 5;\n" STEP(4, 3, 0, ph, 1, ps, "", "")
                 "bra LOOP;\n"
                 "END:\n" P4B "}" STEP_ARGS(0));
}
__device__ __forceinline__ void gemm2(float (&d)[128], Ring& r, uint64_t ha, uint64_t hb, int wg) {
    asm volatile(STEP_REGS "mov.b32 k, 0; mov.b32 ph, 0; add.u32 t, %131, 16;\n"
                 "pmevent 1; bar.sync 2, 256;\n" FIRST_WAIT
                 "LOOP: setp.ne.u32 pa, k, 0; and.pred pr, pa, ps; setp.eq.u32 pl, k, 5;\n"
                 STEP(2, 1, 3, ph, pa, pr, "", "") STEP(3, 2, 4, ph, 1, ps, "", "") "xor.b32 ph, ph, 1; add.u32 k, k, 1;\n" STEP(4, 3, 0, ph, 1, ps, "", "")
                 "@pl bra END;\n" STEP(0, 4, 1, ph, 1, ps, "", "") STEP(1, 0, 2, ph, 1, ps, "", "")
                 "bra LOOP;\n"
                 "END: }" STEP_ARGS(1));
}
template <int O, int K, int J> __device__ __forceinline__ void mma_h(float (&y)[128], uint64_t a, uint64_t b) { mma128_ss<O, 1, 0>(y, a + SL(K) * 2048 + O * 8 + 128 * J, b + SL(K) * 2048 + 2 * J, 1); }
template <int O, int K> __device__ __forceinline__ void half_step(float (&y)[128], uint64_t a, uint64_t b) { mma_h<O, K, 0>(y, a, b); mma_h<O, K, 1>(y, a, b); mma_h<O, K, 2>(y, a, b); mma_h<O, K, 3>(y, a, b); }
template <int R, int U> __device__ __forceinline__ void out_piece(float (&y)[128], const uint32_t (&dd)[16], uint32_t x0, uint32_t x1, float* op) {
    const int i = 64 * (R >> 1) + 8 * U + 2 * (R & 1);
    asm("mul.rn.bf16x2 %0, %0, %1;" : "+r"(x0) : "r"(dd[2 * U]));
    asm("mul.rn.bf16x2 %0, %0, %1;" : "+r"(x1) : "r"(dd[2 * U + 1]));
    asm volatile("st.global.v4.f32 [%0], {%1,%2,%3,%4};" ::"l"(op + (32 * (R & 1) + 16 * (R >> 1)) * 2048 + 16 * U),
                 "f"(y[i] + __uint_as_float(x0 << 16)), "f"(y[i + 1] + __uint_as_float(x0 & 0xffff0000u)),
                 "f"(y[i + 4] + __uint_as_float(x1 << 16)), "f"(y[i + 5] + __uint_as_float(x1 & 0xffff0000u)) : "memory");
}
template <int R, int U0> __device__ __forceinline__ void load_x4(uint32_t (&xx)[8], uint32_t xa) {
#pragma unroll
    for (int u = 0; u < 4; u++)
        asm volatile("ld.shared.v2.b32 {%0,%1}, [%2];" : "=r"(xx[2 * u]), "=r"(xx[2 * u + 1]) : "r"((xa ^ (u << 5)) + (3 - R) * 8192 + U0 * 1024) : "memory");
}
__device__ __forceinline__ Ring ring_at(uint32_t sb, int k) {
    Ring r;
    r.n = 0;
    r.full = sb + OFF_BAR + B_FULL;
    asm("mapa.shared::cluster.u32 %0, %1, %2;" : "=r"(r.rel) : "r"(sb + OFF_BAR + B_EMPTY), "r"((threadIdx.x >> 5) & 1));
    r.sig = __shfl_sync(~0u, threadIdx.x & 95, threadIdx.x) == 0;
    return r;
}

template <bool BY_SM> __global__ void __cluster_dims__(2, 1, 1) __launch_bounds__(512, 1)
fused_kernel(const __grid_constant__ CUtensorMap tmX, const __grid_constant__ CUtensorMap tmBre, const __grid_constant__ CUtensorMap tmBim,
             const __grid_constant__ CUtensorMap tmCre, const __grid_constant__ CUtensorMap tmCim, const __grid_constant__ CUtensorMap tmXd,
             const __grid_constant__ CUtensorMap tmUst, const __grid_constant__ CUtensorMap tmVst,
             const __grid_constant__ CUtensorMap tmWr, const __grid_constant__ CUtensorMap tmWi, const __grid_constant__ CUtensorMap tmXa,
             const Params p) {
    extern __shared__ __align__(1024) uint8_t smraw[];
    asm volatile(".reg .pred pk, p0;");
    const int tid = threadIdx.x, rank = blockIdx.x & 1;
    const uint32_t wi = __shfl_sync(~0u, smem_u32(smraw) + (tid >> 5), 0), sb = wi & ~15u, bars = sb + OFF_BAR;
    const int wg = (wi >> 2) & 3, w = wi & 3, lane = tid & 31, g = lane >> 2, q = lane & 3;
    if (wg != 3) asm volatile("barrier.cluster.arrive.relaxed.aligned; barrier.cluster.wait.aligned;" ::: "memory");
    else asm volatile("prefetch.tensormap [%0];" ::"l"(w == 0 ? &tmX : w == 1 ? &tmBre : &tmBim) : "memory");
    int role;
    {
        uint32_t T = blockIdx.x;
        if (BY_SM) asm("mov.u32 %0, %%smid;" : "=r"(T));
        T >>= 1;
        const uint32_t a = ((T - 32) * 37) >> 8;
        asm("{.reg .pred p; setp.lt.u32 p, %1, 62; selp.u32 %0, 4, -58, p; add.u32 %0, %0, %1;\n"
            "setp.lt.u32 p, %1, 60; selp.u32 %0, %2, %0, p; setp.lt.u32 p, %1, 32; selp.u32 %0, %3, %0, p;}"
            : "=&r"(role) : "r"(T), "r"(8 * (T - 31 - 7 * a) + 4 + a), "r"(8 * (T & 7) + (T >> 3)));
        role = 2 * role + rank;
    }
    const bool spare = role >= 128;
    const int tc = ((role >> 3) & 14) + rank, cb = (role >> 1) & 7;
    const int fb = role >> 5, fcb = role & 31, fpos = pos_of(fcb);
    const int nu = role == 128 ? 1 : (fcb || !role ? 2 : 0);

    if (wg == 3) {
        if (elect_one()) {
            const uint32_t b = bars + w * 8;
            STAMP5(57);
            mbar_init(b, 1);
            if (w < 3 && !spare) {
                mbar_expect_tx(b, 32768);
                tma5d(sb + w * 32768 + 16384, &tmX, w * 64, 0, 0, 0, tc, b);
                if (w == 0) { tma4d(sb, &tmBre, 0, 0, 0, cb * 4, b); tma4d(sb + 8192, &tmBim, 0, 0, 0, cb * 4, b); }
                STAMP5(58);
            }
#pragma unroll
            for (int o = 32; o < B_EPOCH; o += 32) mbar_init(b + o, o < B_EMPTY ? 1 : (o < B_STG ? 2 : (o < B_P3M ? 4 : 8)));
            asm volatile("fence.mbarrier_init.release.cluster;" ::: "memory");
        }
        __syncwarp();
        STAMP5(59);
        asm volatile("barrier.cluster.arrive.relaxed.aligned;" ::: "memory");
    }
    if (opaque32(wg) == 3) {
        asm volatile("setmaxnreg.dec.sync.aligned.u32 24;");
        asm volatile("barrier.cluster.wait.aligned;" ::: "memory");
        if (w == 0) {
            if (!spare && elect_one()) {
                STAMP(56);
#pragma unroll 1
                for (int k = 1; k < NST; k++) {
                    if (k >= 3) mbar_expect_tx(bars + B_FULL + k * 8, 32768);
                    tma4d_mc(sb + k * 32768 + rank * 8192, rank ? &tmBim : &tmBre, k * 64, 0, 0, cb * 4, bars + B_FULL + k * 8);
                    if (k >= 3) tma5d(sb + k * 32768 + 16384, &tmX, k * 64, 0, 0, 0, tc, bars + B_FULL + k * 8);
                }
#define RING_WAIT "mbarrier.try_wait.parity.shared::cta.b64 p, [fb + 256], ph; @p bra GO;\n" \
                  "WAIT: mbarrier.try_wait.parity.shared::cta.b64 p, [fb + 256], ph; add.u32 n, n, 1; setp.gt.or.u32 p, n, 32768, p; @!p bra WAIT;\nGO:\n"
#define RING_NEXT "pmevent 1; add.u32 o, o, 8; setp.eq.u32 p, o, 40; selp.u32 o, 0, o, p; @p xor.b32 ph, ph, 1; add.u32 fb, %1, o; shl.b32 t, o, 12; add.u32 da, %0, t;\n"
                asm volatile("{.reg .b32 o, k, kk, c2, da, db, fb, ph, n, t; .reg .pred p;\n"
                             "mov.b32 o, 0; mov.b32 k, 320; mov.b32 kk, 320; mov.b32 c2, 0; mov.b32 ph, 0; mov.b32 n, 0; mov.b32 fb, %1; mov.b32 da, %0; mov.b32 db, %2;\n"
                             "LOOP:\n" RING_WAIT
                             "cp.async.bulk.tensor.5d.shared::cluster.global.mbarrier::complete_tx::bytes [da], [%3, {kk,0,0,0,%5}], [fb];\n"
                             "cp.async.bulk.tensor.4d.shared::cluster.global.mbarrier::complete_tx::bytes.multicast::cluster [db], [%4, {kk,0,c2,%6}], [fb], %7;\n"
                             "mbarrier.arrive.expect_tx.shared::cta.b64 _, [fb], 32768;\n" RING_NEXT
                             "add.u32 db, %2, t; add.u32 k, k, 64; and.b32 kk, k, 1023; shr.u32 c2, k, 9; and.b32 c2, c2, 2; setp.ne.u32 p, k, 2048; @p bra LOOP;}"
                             ::"r"(sb + 16384), "r"(bars + B_FULL), "r"(sb + rank * 8192), "l"(&tmX), "l"(rank ? &tmBim : &tmBre), "r"(tc), "r"(cb * 4), "h"((uint16_t)3) : "memory");
                asm volatile("{.reg .b32 o, k, kk, da, db, fb, hb, ph, n, t; .reg .b64 m, src; .reg .pred p;\n"
                             "mov.b32 o, 16; mov.b32 k, 0; mov.b32 kk, 0; mov.b32 ph, 1; mov.b32 n, 0; add.u32 fb, %1, 16; add.u32 hb, %1, 72; add.u32 da, %0, 65536; add.u32 db, %2, 65536;\n"
                             "mov.b64 m, %3; mov.b64 src, %5;\n"
                             "GROUP: add.u32 t, %8, k;\n"
                             "OWN: mbarrier.try_wait.parity.shared::cta.b64 p, [t], 0; add.u32 n, n, 1; setp.gt.or.u32 p, n, 32768, p; @!p bra OWN;\n"
                             "LOOP:\n" RING_WAIT
                             "cp.async.bulk.shared::cluster.global.mbarrier::complete_tx::bytes [da], [src], 16384, [hb];\n"
                             "cp.async.bulk.tensor.5d.shared::cluster.global.mbarrier::complete_tx::bytes.multicast::cluster [db], [m, {kk,0,0,0,%6}], [fb], %7;\n"
                             "mbarrier.expect_tx.shared::cta.b64 [fb], 16384; mbarrier.arrive.expect_tx.shared::cta.b64 _, [hb], 16384;\n" RING_NEXT
                             "add.u32 db, %2, t; add.u64 src, src, 16384; sub.u64 m, %4, m; add.u32 k, k, 1; shl.b32 kk, k, 5; and.b32 kk, kk, 0x7c0;\n"
                             "and.b32 t, k, 1; mad.lo.u32 hb, t, 8, fb; add.u32 hb, hb, o; add.u32 hb, hb, 40;\n"
                             "and.b32 t, k, 7; setp.ne.u32 p, t, 0; @p bra LOOP; setp.ne.u32 p, k, 32; @p bra GROUP;}"
                             ::"r"(sb), "r"(bars + B_FULL), "r"(sb + 16384 + rank * 8192), "l"(&tmCre), "l"((uint64_t)&tmCre + (uint64_t)&tmCim),
                               "l"(g_H + (size_t)tc * 32 * 16384), "r"(cb * 8 + rank * 4), "h"((uint16_t)3), "r"(bars + B_HOWN) : "memory");
            }
        } else if (opaque32(w) == 1) {
            const unsigned ep = ld_rlx(g_epoch + role * 8) + 1;
            __syncwarp();
            if (elect_one()) {
                asm volatile("st.relaxed.gpu.global.u32 [%0], %1;" ::"l"(g_epoch + role * 8), "r"(ep) : "memory");
                asm volatile("st.shared.u32 [%0], %1;" ::"r"(bars + B_EPOCH), "r"(ep) : "memory");
                mbar_arrive(bars + B_EP);
            }
            int slot;
            const int kap1 = unit_of(role, 1, slot);
            uint32_t lph = 0;
            if (!spare) mbar_wait(bars + B_STGU, 0);
            STAMP(21);
            const int c0 = fb * 2048 + fpos * 64;
            if (elect_one()) {
                if (!spare) {
#pragma unroll 1
                    for (int r = 4; r < 8; r++) bulk_st(g_X + r * (32 * 16384) + c0 * 2, sb + OFF_P + r * 4096, 128);
                    tma2d_st(&tmUst, c0, 0, sb + OFF_P);
                    bulk_commit();
                    tma2d_st(&tmUst, c0, 64, sb + OFF_P + 8192);
                    bulk_commit();
                    asm volatile("cp.async.bulk.wait_group.read 1;" ::: "memory");
                    red_hint(g_cnt);
                }
            }
            STAMP(40);
#pragma unroll 1
            for (int e = 0; e < 4; e++) {
                if (e >= 2) {
                    if (e == nu) {
                        mbar_wait(bars + B_WFREE, !spare);
                        if (elect_one()) load_w_rows(sb + OFF_WD, &tmWr, &tmWi, kap1, bars + B_WD);
                    }
                    if (e - 2 < nu) mbar_wait(bars + B_STG, e & 1);
                    STAMPO(23, e - 2);
                    if (e == nu && elect_one()) {
                        const int c = (role ? slot : 256) * 32;
                        tma2d_st(&tmVst, c, 0, sb + OFF_P);
                        tma2d_st(&tmVst, c + 4096, 0, sb + OFF_P + 8192);
                        bulk_commit();
                        if (role) { bulk_wait_read(); red_hint(g_cnt + 64); } else bulk_wait_all();
                    }
                    if (e == 3 && !spare && elect_one()) {
                        mbar_expect_tx(bars + B_FG, 8192);
                        bulk_ld(sb + OFF_F, (const uint8_t*)g_tab + TAB_G + fb * 8192, 8192, bars + B_FG);
                    }
                }
                const uint32_t tg = e < 2 ? lane * 128 + ((((lane >> 1) & 2) ^ (lane & 3)) << 4) + (lane >> 3) * 4 : lane * 64 + (lane & 8) * 4 + (lane & 2) * 8 + (lane & 4) * 2;
                if (spare) {
                    if (e == 1) {
                        wait_cnt(g_cnt, 128 * ep);
                        STAMP(42);
#pragma unroll 1
                        for (int n = 0; n < 4096; n++) {
                            if (elect_one()) {
                                mbar_expect_tx(bars + B_LD, 8 * 16384);
#pragma unroll 1
                                for (int r = 0; r < 8; r++) bulk_ld(sb + r * 16384, g_X + (size_t)r * (32 * 16384), 16384, bars + B_LD);
                            }
                            mbar_wait(bars + B_LD, n & 1);
                            bool ok = true;
#pragma unroll 1
                            for (int r = 0; r < 8; r++) ok &= tags_ok<4096>(sb + r * 16384 + tg, ep);
                            if (ok) break;
                        }
                        if (elect_one()) mbar_arrive(bars + B_RAW);
                    }
                } else {
                    const uint32_t dst = sb + OFF_P + (e & 1) * 16384;
#define X_ST1
#define X_ST2
#define X_RETRY
#define X_ARG
                    asm volatile("{.reg .b32 n, a, v0, v1, v2, v3; .reg .pred p, pe, pu;\n"
                                 "elect.sync _|pe, 0xffffffff; setp.lt.u32 pu, %10, 2; mov.b32 n, 0; pmevent 1;\n"
                                 "POLL: ld.relaxed.gpu.global.u32 v0, [%1]; setp.eq.u32 p, v0, %2; @p bra LOAD;\n"
                                 "nanosleep.u32 20; add.u32 n, n, 1; setp.lt.u32 p, n, 32768; @p bra POLL;\n"
                                 "LOAD:\n" X_ST1 "cp.async.bulk.wait_group.read 0;\n"
                                 "@pe cp.async.bulk.shared::cluster.global.mbarrier::complete_tx::bytes [%3], [%4], 16384, [%5]; @pe mbarrier.arrive.expect_tx.shared::cta.b64 _, [%5], 16384;\n"
                                 "mov.b32 a, 0;\n"
                                 "WAIT: mbarrier.try_wait.parity.shared::cta.b64 p, [%5], %0; @p bra CHECK; add.u32 n, n, 1; setp.lt.u32 p, n, 65536; @p bra WAIT;\n"
                                 "CHECK:\n" X_ST2 "@pu bra FOUR;\n"
                                 "ld.shared.u32 a, [%7]; ld.shared.u32 v0, [%6 + 2048]; ld.shared.u32 v1, [%6 + 6144]; ld.shared.u32 v2, [%6 + 10240]; ld.shared.u32 v3, [%6 + 14336];\n"
                                 "lop3.b32 a, a, v0, %8, 0x7e; lop3.b32 v1, v1, v2, %8, 0x7e; lop3.b32 a, a, v3, %8, 0xf6; or.b32 a, a, v1;\n"
                                 "FOUR: ld.shared.u32 v0, [%6]; ld.shared.u32 v1, [%6 + 4096]; ld.shared.u32 v2, [%6 + 8192]; ld.shared.u32 v3, [%6 + 12288];\n"
                                 "lop3.b32 a, a, v0, %8, 0xf6; lop3.b32 a, a, v1, %8, 0xf6; lop3.b32 v2, v2, v3, %8, 0x7e; lop3.b32 a, a, v2, 1, 0xa8;\n"
                                 "setp.eq.u32 p, a, 0; vote.sync.all.pred p, p, -1; @p bra OK;\n" X_RETRY
                                 "add.u32 n, n, 16; setp.ge.u32 p, n, 65536; @p bra OK; xor.b32 %0, %0, 1; bra LOAD;\n"
                                 "OK: @pe mbarrier.arrive.shared::cta.b64 _, [%9]; pmevent 1; xor.b32 %0, %0, 1;}"
                                 : "+r"(lph)
                                 : "l"(g_cnt + e * 32), "r"(128 * ep), "r"(dst), "l"(g_X + (size_t)(e < 2 ? role + e * 128 : 254 + (fb * 32 + fpos) * 2 + e) * 16384), "r"(bars + B_LD),
                                   "r"(dst + tg), "r"(dst + (e == 3 ? (lane & 1) * 8192 + 32 : 0)), "r"(ep), "r"(bars + B_IN + e * 8), "r"(e) X_ARG : "memory");
                }
                if (e < 2 && elect_one()) {
                    if (e) prefetch_w_rows(&tmWr, &tmWi, kap1);
                    else {
                        if (!spare) {
                            tma2d_st(&tmUst, c0, 128, sb + OFF_P + 16384);
                            tma2d_st(&tmUst, c0, 192, sb + OFF_P + 24576);
                            bulk_commit();
                            bulk_wait_read();
                            red_hint(g_cnt + 32);
                        }
                    }
                }
            }
            if (!spare) {
                mbar_wait(bars + B_HOWN + 8, 0);
#pragma unroll 1
                for (int r = 0; r < 4; r++) {
                    if (r == 3) mbar_wait(bars + B_P3M, 0);
                    if (elect_one()) {
                        if (r == 0) { mbar_expect_tx(bars + B_XD, 24576 + 256); mbar_expect_tx(bars + B_XD + 8, 8192); bulk_ld(sb + OFF_LAM, p.dsk + cb * 128, 256, bars + B_XD); }
                        tma4d(sb + OFF_F + (3 - r) * 8192, &tmXd, 0, tc * 128 + 32 * (r & 1) + 16 * (r >> 1), 0, cb * 2, bars + B_XD + (r == 3) * 8);
                    }
                    __nanosleep(PACE_X);
                }
            }
        } else {
            if (w == 2) {
                {
                    const int u = lane >> 4;
                    int slot;
                    const int r0 = unit_of(role, u, slot) + 512 * ((lane >> 1) & 3), r1 = (2048 - r0) & 2047, mir = (lane >> 3) & 1;
                    const unsigned short* wp = (const unsigned short*)((lane & 1) ? p.wi : p.wr);
                    const float a = bf2f(wp[r0 * 513 + mir * 512]), b = bf2f(wp[r1 * 513 + mir * 512]);
                    asm volatile("st.shared.f32 [%0], %1;" ::"r"(sb + OFF_WSP + u * 64 + (lane & 15) * 4), "f"(0.5f * ((lane & 1) ? (mir ? b - a : a - b) : a + b)) : "memory");
                }
                warp_arrive(bars + B_WSP);
                int slot;
                const int kap = unit_of(role, 0, slot);
                if (!spare) mbar_wait(bars + B_WFREE, 0);
                if (elect_one()) {
                    mbar_expect_tx(bars + B_FG, 8192);
                    bulk_ld(sb + OFF_F, (const uint8_t*)g_tab + TAB_FG, 8192, bars + B_FG);
                    mbar_expect_tx(bars + B_WD, 16 * WPITCH);
                }
#pragma unroll 1
                for (int i = 0; i < 4 && nu; i++) {
                    if (WN == 1 || !(i & 1)) __nanosleep(WT0);
                    if (elect_one()) tma2d(sb + OFF_WD + i * 4 * WPITCH, (i & 1) ? &tmWi : &tmWr, ((i < 2 ? kap : (512 - kap) & 511) * 1026 >> 4) * 2, 0, bars + B_WD);
                }
            } else if (!spare) {
#pragma unroll 1
                for (int i = 0; i < 8; i++) {
                    if (i >= XA_N0) __nanosleep(XA_PACE);
                    if (elect_one()) {
                        const uint32_t xb = bars + (i < 4 ? B_RAW : B_XIN);
                        if (!(i & 3)) mbar_expect_tx(xb, 16384);
                        tma3d(sb + OFF_F + i * 4096, &tmXa, fcb * 32, 0, 4 * i + fb, xb);
                    }
                }
            }
            if (!spare) {
                const unsigned ep = get_epoch(bars);
#define CNT_RETRY
#define CNT_ARG
                asm volatile("{.reg .b32 o, k, hb, fb, ca, m, ph, rph, n, t, v0, v1, v2, v3; .reg .b64 src; .reg .pred p, pe;\n"
                             "elect.sync _|pe, 0xffffffff; mov.b32 o, %0; shr.u32 k, %0, 3; sub.u32 k, k, 2; mov.b32 m, 0x107c0; mov.b32 rph, 0; mov.b32 n, 0;\n"
                             "bra NEXT;\n"
                             "LOOP: mbarrier.try_wait.parity.shared::cta.b64 p, [hb], ph; @p bra GO;\n"
                             "WAIT: mbarrier.try_wait.parity.shared::cta.b64 p, [hb], ph; add.u32 n, n, 1; setp.gt.or.u32 p, n, 32768, p; @!p bra WAIT;\n"
                             "GO: ld.shared.u32 v0, [ca]; ld.shared.u32 v1, [ca + 128]; ld.shared.u32 v2, [ca + 256]; ld.shared.u32 v3, [ca + 384];\n"
                             "lop3.b32 v0, v0, v1, %4, 0x7e; lop3.b32 v2, v2, v3, %4, 0x7e; lop3.b32 v0, v0, v2, 1, 0xa8; setp.eq.u32 p, v0, 0; vote.sync.all.pred p, p, -1; @p bra OK;\n"
                             CNT_RETRY "add.u32 n, n, 16; setp.gt.u32 p, n, 32768; @p bra OK;\n"
                             "shl.b32 t, o, 12; add.u32 t, t, %5; mad.wide.u32 src, k, 16384, %6;\n"
                             "@pe mbarrier.arrive.expect_tx.shared::cta.b64 _, [%7], 16384; @pe cp.async.bulk.shared::cluster.global.mbarrier::complete_tx::bytes [t], [src], 16384, [%7];\n"
                             "AGAIN: mbarrier.try_wait.parity.shared::cta.b64 p, [%7], rph; add.u32 n, n, 1; setp.gt.or.u32 p, n, 32768, p; @!p bra AGAIN;\n"
                             "xor.b32 rph, rph, 1; bra GO;\n"
                             "OK: @pe mbarrier.arrive.shared::cta.b64 _, [fb]; pmevent 1;\n"
                             "add.u32 o, o, 16; setp.ge.u32 p, o, 40; @p sub.u32 o, o, 40; add.u32 k, k, 2;\n"
                             "NEXT: shr.u32 m, m, 1; and.b32 ph, m, 1; add.u32 fb, %1, o; mad.lo.u32 hb, o, 2, %2; mad.lo.u32 ca, o, 4096, %3; setp.lt.u32 p, k, 32; @p bra LOOP;}"
                             ::"r"(8 * w), "r"(bars + B_FULL), "r"(bars + B_HL - 16 + w * 8), "r"(sb + (q >> 1) * 8192 + (q & 1) * 512 + g * 1040 + q * 4), "r"(ep),
                               "r"(sb), "l"(g_H + (size_t)tc * 32 * 16384), "r"(bars + B_HR - 16 + w * 8) CNT_ARG : "memory");
                if (w == 3) warp_arrive(bars + B_DONE);
            }
        }
    } else {
        STAMP(55);
        asm volatile("setmaxnreg.inc.sync.aligned.u32 152;");
        STAMP5(60);
        const int t7 = tid & 127, hf = wg - 1;
        const int mi = lane >> 3, gl = lane & 7;
        if (spare && wg != 2) {
            if (tid < 64) { const uint4 v = __ldg((const uint4*)((const uint8_t*)g_tab + TAB_PC) + tid); sts128(sb + OFF_LAM + tid * 16, v.x, v.y, v.z, v.w); }
            bar_sync(1, 256);
            mbar_wait(bars + B_RAW, 0);
            STAMP(0);
#pragma unroll 1
            for (int u = 0; u < nu; u++) {
                int slot;
                const int t = unit_of(role, u, slot) >> 5;
                const uint32_t off = (tid >> 2) * 128 + q * 16;
                float zr[16], zi[16];
#pragma unroll
                for (int k = 0; k < 16; k++) zr[k] = zi[k] = 0.f;
#pragma unroll 1
                for (int r = (t & 1) ? 0 : t >> 1; r < 8 - ((t & 1) ? 0 : (t >> 1) - 1); r += (t & 1) ? 1 : 8 - t) {
                    float4 c;
                    float a[8], b[8];
                    lds128f(sb + OFF_LAM + t * 128 + r * 16, c.x, c.y, c.z, c.w);
                    lds128f(sb + r * 16384 + off, a[0], a[1], a[2], a[3]);
                    lds128f(sb + r * 16384 + off + 64, b[0], b[1], b[2], b[3]);
                    lds128f(sb + r * 16384 + off + 8192, a[4], a[5], a[6], a[7]);
                    lds128f(sb + r * 16384 + off + 8192 + 64, b[4], b[5], b[6], b[7]);
#pragma unroll
                    for (int k = 0; k < 16; k++) {
                        const uint32_t ua = __float_as_uint(a[k >> 1]), ub = __float_as_uint(b[k >> 1]);
                        const float x = __uint_as_float((k & 1) ? ua & 0xffff0000u : ua << 16), y = __uint_as_float((k & 1) ? ub & 0xffff0000u : ub << 16);
                        zr[k] = fmaf(c.x, x, fmaf(c.z, y, zr[k]));
                        zi[k] = fmaf(c.y, x, fmaf(c.w, y, zi[k]));
                    }
                }
                const uint32_t dst = sb + OFF_P + u * 16384 + off;
#pragma unroll
                for (int k = 0; k < 16; k += 8) {
                    sts128(dst + k * 1024, pk(zr[k], zr[k + 1]), pk(zr[k + 2], zr[k + 3]), pk(zr[k + 4], zr[k + 5]), pk(zr[k + 6], zr[k + 7]));
                    sts128(dst + k * 1024 + 64, pk(zi[k], zi[k + 1]), pk(zi[k + 2], zi[k + 3]), pk(zi[k + 4], zi[k + 5]), pk(zi[k + 6], zi[k + 7]));
                }
                fence_async_sm();
                bar_sync(1, 256);
                if (tid == 0) mbar_arrive(bars + B_IN + u * 8);
                STAMPO(1, u);
            }
            return;
        }
        if (wg == 2 && !spare) {
            asm volatile("setmaxnreg.inc.sync.aligned.u32 176;");
            uint32_t f1[16];
            cf tw[8];
            if (TAB_T0) __nanosleep(TAB_T0);
            ldtab<4, 2048>(f1, TAB_F1 + t7 * 16);
            ldtab_cf<16>(tw, TAB_TW1 + (t7 >> 2) * 64);
            const uint32_t ep = get_epoch(bars);
            uint32_t a0 = sb + OFF_P + (8 * w + gl + 32 * (mi >> 1)) * 128 + (((((mi & 1) << 2) | (fpos & 3)) ^ gl) << 4);
            float acc[128];
            const uint64_t dx = opaque(mkdesc(sb + OFF_F, 4096, 512, 2));
            mbar_wait(bars + B_RAW, 0);
            pinu(f1);
            wg_fence();
#pragma unroll
            for (int j = 0; j < 4; j++) mma128_rs<0, 1>(acc, f1[4 * j], f1[4 * j + 1], f1[4 * j + 2], f1[4 * j + 3], dx + j * 64, j);
            wg_commit();
            mbar_wait(bars + B_XIN, 0);
            wg_fence();
            STAMP(20);
#pragma unroll
            for (int j = 0; j < 4; j++) mma128_rs<64, 1>(acc, f1[4 * j], f1[4 * j + 1], f1[4 * j + 2], f1[4 * j + 3], dx + 1024 + j * 64, j);
            wg_commit();
            wg_wait<0>();
            pin(acc);
            pinu(f1);
            warp_arrive(bars + B_WFREE);
#pragma unroll 1
            for (int h = 0;; h++) {
                const uint32_t tmask = 2 * q + h == fpos >> 2 ? ~1u : ~0u, tbit = ep & ~tmask;
#pragma unroll
                for (int cl = 0; cl < 2; cl++) {
                    c2 v[8];
#pragma unroll
                    for (int n = 0; n < 8; n++) {
                        const int i = 4 * (4 * n + cl);
                        v[n] = {{acc[i], acc[i + 2]}, {acc[i + 1], acc[i + 3]}};
                    }
                    dft8<true, YP1>(v, tw);
#pragma unroll
                    for (int r = 0; r < 8; r += 2) {
                        uint32_t o0 = pk(v[r].a.x, v[r].b.x), o1 = pk(v[r].a.y, v[r].b.y), o2 = pk(v[r + 1].a.x, v[r + 1].b.x), o3 = pk(v[r + 1].a.y, v[r + 1].b.y);
                        if (cl == 0) { o0 = (o0 & tmask) | tbit; o2 = (o2 & tmask) | tbit; }
                        stsm4((a0 ^ (cl << 4)) + r * 4096, o0, o1, o2, o3);
                    }
                }
                if (h) break;
                a0 ^= 32;
#pragma unroll
                for (int n = 0; n < 8; n++) {
                    asm volatile("mov.b32 %0, %8; mov.b32 %1, %9; mov.b32 %2, %10; mov.b32 %3, %11; mov.b32 %4, %12; mov.b32 %5, %13; mov.b32 %6, %14; mov.b32 %7, %15; pmevent 1;"
                                 : "=&f"(acc[16 * n]), "=&f"(acc[16 * n + 1]), "=&f"(acc[16 * n + 2]), "=&f"(acc[16 * n + 3]), "=&f"(acc[16 * n + 4]), "=&f"(acc[16 * n + 5]), "=&f"(acc[16 * n + 6]), "=&f"(acc[16 * n + 7])
                                 : "f"(acc[16 * n + 8]), "f"(acc[16 * n + 9]), "f"(acc[16 * n + 10]), "f"(acc[16 * n + 11]), "f"(acc[16 * n + 12]), "f"(acc[16 * n + 13]), "f"(acc[16 * n + 14]), "f"(acc[16 * n + 15]));
                }
            }
            fence_async_sm();
            warp_arrive(bars + B_STGU);
            bar_sync(3, 128);
            asm volatile("setmaxnreg.dec.sync.aligned.u32 152;");
            bar_arrive(7, 256);
        }
        if (wg == 1) {
            if (LAM_T0) __nanosleep(LAM_T0);
            const int cl = tid & 127, ch = (cl >> 6) * 512 + ((cl >> 3) & 1) * 256 + cb * 32 + ((cl >> 4) & 3) * 8 + (cl & 7);
            const float lr = bf2f(*(const unsigned short*)padd(p.lre, 2 * ch)), li = bf2f(*(const unsigned short*)padd(p.lim, 2 * ch));
            const float dt = __bfloat162float(__float2bfloat16(expf(bf2f(*(const unsigned short*)padd(p.ldt, 2 * ch)))));
            const float an = dt * li, th = an * 0.318309873342514f;
            float sn, cs, inv;
            sincospif(fmaf(rintf(0.5f * th), -2.f, th) + fmaf(an, 1.2841276653e-8f, fmaf(an, 0.318309873342514f, -th)), &sn, &cs);
            const float ex = expf(dt * lr), br = ex * cs, bi = ex * sn;
            asm("rcp.approx.f32 %0, %1;" : "=f"(inv) : "f"(lr * lr + li * li));
            inv += inv;
            const float cr = ((br - 1.f) * lr + bi * li) * inv, ci = (bi * lr - (br - 1.f) * li) * inv;
            sts128(sb + OFF_LAM + cl * 16, __float_as_uint(br), __float_as_uint(-bi), __float_as_uint(cr), __float_as_uint(-ci));
            mbar_wait(bars + B_EP, 0);
            bar_sync(8, 128);
            if (tid == 128) mbar_arrive(bars + B_LAM);
        }
        if (wg != 2) {
        if (wg == 0) bar_sync(4, 128); else bar_sync(7, 256);
        asm volatile("setmaxnreg.inc.sync.aligned.u32 160;");
        if (wg == 0) bar_sync(4, 128);
        float d[128];
        STAMPW(0, 10);
        Ring rg = ring_at(sb, role * 66 + wg * 16);
        cf lam[2];
        unsigned ep;
        gemm1(d, rg, ring_desc(sb, 0, 16, 1), ring_desc(sb, 16384, 16, 1), wg);
        const uint32_t lama = sb + OFF_LAM + wg * 1024 + w * 256 + (fresh_lane() & 28) * 4;
        mbar_wait_fast(bars + B_LAM, 0);
        lam[0] = lds_cf(lama); lam[1] = lds_cf(lama + 128);
        asm volatile("ld.shared.u32 %0, [%1];" : "=r"(ep) : "r"(bars + B_EPOCH) : "memory");
        asm volatile("setmaxnreg.inc.sync.aligned.u32 176;");
        cf L[2] = {lam[0], lam[1]};
#pragma unroll
        for (int i = 0; i < 4; i++) { L[0] = csq(L[0]); L[1] = csq(L[1]); }
        asm volatile("" : "+f"(L[0].x), "+f"(L[0].y), "+f"(L[1].x), "+f"(L[1].y)::"memory");
        wg_wait<0>();
        ring_release(rg, 8 * wg);
        pin(d);
        STAMPW(1, 11);
        {
            const int lane = fresh_lane(), g = lane >> 2, q = lane & 3, mi = lane >> 3, gl = lane & 7;
            cf f[2], fb2[2];
#pragma unroll
            for (int i = 0; i < 17; i++) {
#pragma unroll
                for (int h = 0; h < 2; h++) {
                    const int r = 4 * (i >> 1) + 2 * h + (i & 1), r2 = 32 + 4 * ((i - 1) >> 1) + 2 * h + ((i - 1) & 1);
                    if (i < 16) f[h] = i ? cfma(lam[h], f[h], {d[r], -d[64 + r]}) : cf{d[r], -d[64 + r]};
                    if (i > 0) fb2[h] = i > 1 ? cfma(lam[h], fb2[h], {d[r2], -d[64 + r2]}) : cf{d[r2], -d[64 + r2]};
                    if (i && (h || !(YS & 8))) YIELD_S1();
                }
            }
            const uint8_t* cbase = (const uint8_t*)g_carry + (tc * 16 + wg * 8 + cb) * 512 + w * 64;
            const uint8_t* cptr = padd(cbase, g * 8);
            const unsigned tag = ep & 15u;
#pragma unroll
            for (int h = 0; h < 2; h++) { f[h] = cfma(L[h], f[h], fb2[h]); L[h] = csq(L[h]); }
            cf s0[2], s1[2], s2[2];
#pragma unroll
            for (int h = 0; h < 2; h++) {
                s0[h] = {__shfl_sync(~0u, f[h].x, 0, 4), __shfl_sync(~0u, f[h].y, 0, 4)};
                s1[h] = {__shfl_sync(~0u, f[h].x, 1, 4), __shfl_sync(~0u, f[h].y, 1, 4)};
                s2[h] = {__shfl_sync(~0u, f[h].x, 2, 4), __shfl_sync(~0u, f[h].y, 2, 4)};
            }
#pragma unroll
            for (int h = 0; h < 2; h++) {
                s1[h] = cfma(L[h], s0[h], s1[h]);
                s2[h] = cfma(L[h], s1[h], s2[h]);
                f[h] = cfma(L[h], s2[h], f[h]);
                asm volatile("{.reg .pred p; .reg .b64 a; setp.eq.u32 p, %3, 3; mov.b64 a, {%1,%2}; @p st.relaxed.gpu.global.b64 [%0], a;}" ::"l"(cptr + h * 256),
                             "r"((__float_as_uint(f[h].x) & ~15u) | tag), "f"(f[h].y), "r"(q) : "memory");
            }
            STAMPX(2, 12);
            cf gam = lds_cf(lama + 8);
            cf st = csel(q & 2, csel(q & 1, s2[0], s1[0]), csel(q & 1, s0[0], {0.f, 0.f}));
            const cf st1 = csel(q & 2, csel(q & 1, s2[1], s1[1]), csel(q & 1, s0[1], {0.f, 0.f}));
            cptr = padd(cbase - 4 * 8192, (3 - mi) * 8192 + gl * 8);
            const int nprev = tc - 1 - mi;
            const uint8_t* hptr = padd(g_H + (size_t)(tc * 32 + wg * 16 + (cb & 6)) * 16384 + ((cb & 1) * 4 + w) * 1024, g * 64 + ((q ^ (g >> 1)) << 4));
            const uint32_t hm = 4 * (g & 1) + (q ^ (g >> 1)) == (cb & 1) * 4 + w ? ~1u : ~0u;
            float u[64];
            uint64_t fv[4] = {tag, tag, tag, tag};
            prescale<0>(u, d, gam);
            gather(fv, cptr, nprev);
#pragma unroll 1
            for (int h = 0;; h++) {
                const cf L2 = csq(L[0]), M = csq(L2);
                cf M4 = csq(csq(M));
                M4 = {__shfl_sync(~0u, M4.x, 4 * gl), __shfl_sync(~0u, M4.y, 4 * gl)};
                cf lq = cmul(gam, cmul(csel(q & 1, L[0], {1.f, 0.f}), csel(q & 2, L2, {1.f, 0.f})));
                st = cmul(gam, st);
                asm volatile("pmevent 1;" : "+f"(lq.x), "+f"(lq.y), "+f"(st.x), "+f"(st.y));
#pragma unroll 1
                for (unsigned n = 0; __any_sync(~0u, (((uint32_t)fv[0] ^ tag) | ((uint32_t)fv[1] ^ tag) | ((uint32_t)fv[2] ^ tag) | ((uint32_t)fv[3] ^ tag)) & 15u) && n < SPIN_LIMIT; n++) gather(fv, cptr, nprev);
                if (!h) STAMPX(53, 54);
                cf P = as_cf(fv[3]), pj[4];
#pragma unroll
                for (int a = 2; a >= 0; a--) P = cfma(M4, P, as_cf(fv[a]));
                cptr += 256;
                asm volatile("" : "+f"(P.x), "+f"(P.y)::"memory");
                gather(fv, cptr, h ? -1 : nprev);
#pragma unroll
                for (int j = 3; j >= 0; j--) pj[j] = {__shfl_sync(~0u, P.x, g + 8 * j), __shfl_sync(~0u, P.y, g + 8 * j)};
                st = cfma(lq, cfma(M, cfma(M, cfma(M, pj[3], pj[2]), pj[1]), pj[0]), st);
                if (!h) STAMPX(3, 13);
                uint32_t keep = sb >> 28;
                scan2(u, lam[0], st, hptr, hm, ep & ~hm, keep);
                warp_arrive(bars + B_HOWN + wg * 16 + h * 8 + keep);
                if (h) break;
                STAMPW(4, 14);
                if (wg == 1 && nu) bar_sync(9, 256);
                lds128f(lama + 128, lam[0].x, lam[0].y, gam.x, gam.y);
                st = st1;
                L[0] = L[1];
                hptr += 8 * 16384;
                prescale<1>(u, d, gam);
            }
            STAMPW(5, 15);
        }
        if (wg == 0) bar_sync(4, 128); else bar_sync(8, 128);
        if (wg == 0) {
            asm volatile("setmaxnreg.dec.sync.aligned.u32 160;");
            float y[128];
            rg = ring_at(sb, role * 66 + 32);
            STAMP(6);
            STAMP(7);
            const uint64_t dA = ring_desc(sb, 0, 512, 2), dB = ring_desc(sb, 16384, 16, 1);
            gemm2(y, rg, dA, dB, 0);
            asm volatile("setmaxnreg.inc.sync.aligned.u32 184;");
            const int lane = fresh_lane(), g = lane >> 2, q = lane & 3;
            const int pg = 2 * (g & 3) + (g >> 2);
            float* op = (float*)padd(p.out + (size_t)(tc * 128 + 64 * (w & 1) + 8 * (w >> 1)) * 2048 + 1024 + cb * 128, pg * 8192 + q * 16);
            const uint32_t xa = sb + OFF_F + (16 * (w & 1) + 8 * (w >> 1) + pg) * 128 + (((q >> 1) ^ pg) << 4) + (q & 1) * 8;
#define HALF0(k) wg_fence(); peek(k < 63 ? rg.full + SL(k + 1) * 8 : bars + B_XD, PH(k + 1)); half_step<0, k>(y, dA, dB); wg_commit(); peek_wait(k < 63 ? rg.full + SL(k + 1) * 8 : bars + B_XD, PH(k + 1), rg.n);
            HALF0(60) HALF0(61) HALF0(62) HALF0(63)
            const uint64_t dB2 = ring_desc(sb >> 1, 16384, 16, 1);
            uint32_t xa0[8], xa1[8], dd[16];
#pragma unroll
            for (int i = 0; i < 8; i++) asm volatile("ld.shared.v2.b32 {%0,%1}, [%2];" : "=r"(dd[2 * i]), "=r"(dd[2 * i + 1]) : "r"(sb + OFF_LAM + q * 8 + 32 * i) : "memory");
            load_x4<0, 0>(xa0, xa);
            wg_fence();
            half_step<64, 64 - SKEW>(y, dA, dB2);
            wg_commit();
            wg_wait<1>();
#pragma unroll
            for (int i = 0; i < 64; i++) asm volatile("" : "+f"(y[i])::"memory");
            STAMP(16);
#define MM(n) if (4 + (n) < 4 * SKEW) { wg_fence(); mma_h<64, 65 - SKEW + (n) / 4, (n) % 4>(y, dA, dB2); mma_h<64, 65 - SKEW + (n) / 4, (n) % 4 + 1>(y, dA, dB2); }
#define OUT4(R, U, X, n) out_piece<R, U>(y, dd, X[0], X[1], op); MM(n) out_piece<R, U + 1>(y, dd, X[2], X[3], op); MM(n + 2) \
                         out_piece<R, U + 2>(y, dd, X[4], X[5], op); MM(n + 4) out_piece<R, U + 3>(y, dd, X[6], X[7], op); MM(n + 6)
            load_x4<0, 4>(xa1, xa);
            OUT4(0, 0, xa0, 0)
            load_x4<1, 0>(xa0, xa);
            OUT4(0, 4, xa1, 8)
            wg_commit();
            load_x4<1, 4>(xa1, xa);
            OUT4(1, 0, xa0, 16)
            load_x4<2, 0>(xa0, xa);
            OUT4(1, 4, xa1, 16)
            STAMP(18);
            wg_wait<0>();
#pragma unroll
            for (int i = 64; i < 128; i++) asm volatile("" : "+f"(y[i])::"memory");
            STAMP(8);
            load_x4<2, 4>(xa1, xa);
            mbar_wait_fast(bars + B_XD + 8, 0);
            OUT4(2, 0, xa0, 16)
            load_x4<3, 0>(xa0, xa);
            OUT4(2, 4, xa1, 16)
            load_x4<3, 4>(xa1, xa);
            OUT4(3, 0, xa0, 16)
            OUT4(3, 4, xa1, 16)
            STAMP(9);
            return;
        }
        asm volatile("setmaxnreg.dec.sync.aligned.u32 152;");
        } else {
        if (nu) {
            cf T[8];
            ldtab_cf<2048>(T, TAB_T + t7 * 16);
            const uint32_t ep = get_epoch(bars);
            const int ka = pos_of(t7 >> 2);
            asm volatile("setp.eq.u32 p0, %0, 0;" ::"r"(__shfl_sync(~0u, t7, lane)));
            mbar_wait(bars + B_WSP, 0);
            mbar_wait(bars + B_FG, 0);
            uint32_t wd[4], wm[4], vo[32];
            const uint8_t* vp;
            int slot;
            const int kap0 = unit_of(role, 0, slot), al = 2 * kap0;
            const int kap1 = __shfl_sync(~0u, unit_of(role, 1, slot), 0);
            slot = __shfl_sync(~0u, slot, 0);
            cf be1 = twid(kap0 + 512 * q, 2048), be2 = csq(be1), be3 = cmul(be1, be2);
#pragma unroll
            for (int j = 0; j < 4; j++) {
                wd[j] = sb + OFF_WD + ((j + q) & 3) * WPITCH + (al & 15) + 2 * ka + 64 * q;
                wm[j] = sb + OFF_WM + (((role ? 3 : 4) - j - q) & 3) * WPITCH + (-al & 15) + 1024 - 2 * ka - 64 * q;
                wd[j] = __shfl_sync(~0u, wd[j], lane);
            }
#pragma unroll 1
            for (int u = 0; u < nu; u++) {
                const uint32_t buf = sb + OFF_P + u * 16384;
                float acc[64], za[32], zb[32], ya[32], yb[32], vv[64];
                const uint64_t dF = opaque(mkdesc(sb + OFF_F, 16, 1024, 1)), dB = opaque(mkdesc(buf, 4096, 512, 2));
                mbar_wait(bars + B_IN + u * 8, 0);
                if (!role) {
                    const uint32_t z = buf + w * 1024 + (fresh_lane() >> 2) * 128 + 64 + (fresh_lane() & 3) * 16;
#pragma unroll
                    for (int i = 0; i < 4; i++) sts128(z + i * 4096, 0, 0, 0, 0);
                    fence_async_sm();
                    bar_sync(3, 128);
                }
                STAMP3(22);
                wg_fence();
#pragma unroll
                for (int j = 0; j < 4; j++) mma128_ss<0, 0, 1>(acc, dF + j * 2, dB + j * 64, j);
                wg_commit();
                if (u) {
                    const uint32_t va = sb + OFF_P + (((uint32_t)(uintptr_t)vp - (uint32_t)(uintptr_t)g_X) >> 9 & 0x7c0) + ((uint32_t)(uintptr_t)vp & 31) + (fresh_lane() & 4) * 8;
                    bar_sync(3, 128);
#pragma unroll
                    for (int k = 0; k < 16; k++) sts64(va + ((k >> 1) & 1) * 8192 + (k >> 2) * 2048 + (k & 1) * 256, vo[2 * k], vo[2 * k + 1]);
                    fence_async_sm();
                    warp_arrive(bars + B_STG);
                    if (!role) { const uint32_t t = wm[0]; wm[0] = wm[1]; wm[1] = wm[2]; wm[2] = wm[3]; wm[3] = t; }
                }
                STAMP3(39);
                wg_wait<0>();
                pin(acc);
                STAMP3(30);
                uint32_t af[16], ag[16];
#pragma unroll
                for (int k = 0; k < 8; k++) {
                    uint32_t(&o)[16] = k < 4 ? af : ag;
                    const int c = k & 3;
#pragma unroll
                    for (int b = 0; b < 2; b++) {
                        const int i = 4 * (4 * ((k >> 2) * 2 + b) + c);
                        c2 x = mul2(c2{{acc[i], acc[i + 2]}, {acc[i + 1], acc[i + 3]}}, c2{T[2 * c], T[2 * c + 1]});
                        o[4 * c + b] = pk(x.a.x, x.a.y);
                        o[4 * c + 2 + b] = pk(x.b.x, x.b.y);
                    }
                    asm volatile("" : "+r"(o[4 * c]), "+r"(o[4 * c + 1]), "+r"(o[4 * c + 2]), "+r"(o[4 * c + 3])::"memory");
                    wg_fence();
                    mma64_rs<0>(k < 4 ? za : zb, o[4 * c], o[4 * c + 1], o[4 * c + 2], o[4 * c + 3], dF + c * 2, c);
                }
                wg_commit();
                STAMP3(31);
                mbar_wait_fast(bars + B_WD, u & 1);
                STAMP3(37);
                uint32_t wr[16];
#pragma unroll
                for (int i = 0; i < 16; i++) wr[i] = lds16(wd[i >> 2] + 256 * ((i >> 1) & 1) + (i & 1) * 4 * WPITCH);
                wg_wait<0>();
                pin(za);
                pin(zb);
                pinu(af);
                pinu(ag);
                STAMP3(32);
#pragma unroll
                for (int jb = 0; jb < 4; jb++) {
                    const int i = 8 * jb;
                    c2 s0 = {{za[i], za[i + 4]}, {za[i + 1], za[i + 5]}}, s2 = {{za[i + 2], za[i + 6]}, {za[i + 3], za[i + 7]}};
                    c2 s1 = {{zb[i], zb[i + 4]}, {zb[i + 1], zb[i + 5]}}, s3 = {{zb[i + 2], zb[i + 6]}, {zb[i + 3], zb[i + 7]}};
                    c2 W[4];
                    auto wcvt = [&](int j) {
                        asm volatile("shl.b32 %0, %4, 16; shl.b32 %1, %5, 16; shl.b32 %2, %6, 16; shl.b32 %3, %7, 16;"
                                     : "=&f"(W[j].a.x), "=&f"(W[j].a.y), "=&f"(W[j].b.x), "=&f"(W[j].b.y) : "r"(wr[4 * j]), "r"(wr[4 * j + 1]), "r"(wr[4 * j + 2]), "r"(wr[4 * j + 3]));
                        if ((jb & 1) == 0)
                            asm volatile("@p0 ld.shared.v2.f32 {%0,%1}, [%2];" : "+f"(W[j].a.x), "+f"(W[j].a.y) : "r"(sb + OFF_WSP + u * 64 + jb * 16 + j * 8));
                        if (jb < 3) {
#pragma unroll
                            for (int k = 4 * j; k < 4 * j + 4; k++) {
                                const int e = (k >> 1) & 1, pl = (k & 1) * 4 * WPITCH;
                                wr[k] = jb == 0 ? lds16(wd[j] + 512 + 256 * e + pl) : lds16(wm[j] - 512 * (jb - 1) - 256 * e + pl);
                            }
                        }
                        if (jb >= 2) { W[j].a.y = -W[j].a.y; W[j].b.y = -W[j].b.y; }
                    };
                    wcvt(0);
                    s2 = mul2(s2, be1);
                    s1 = fma2(s1, be2, s0);
                    wcvt(1);
                    s3 = fma2(s3, be3, s2);
                    { const c2 x = twm2(s0, s1), y = twm2(s2, s3); s0 = s1; s2 = s3; s1 = x; s3 = y; }
                    wcvt(2);
                    bfly<0>(s0, s2); bfly_mi<0>(s1, s3);
                    wcvt(3);
                    s0 = mul2(s0, W[0]); s1 = mul2(s1, W[1]);
                    bfly_tw<0>(s0, s2, W[2], s1, s3, W[3]);
                    bfly<0>(s0, s1); bfly_mi<0>(s2, s3);
                    af[4 * jb] = pk(s0.a.x, s0.b.x); af[4 * jb + 1] = pk(s3.a.x, s3.b.x); af[4 * jb + 2] = pk(s0.a.y, s0.b.y); af[4 * jb + 3] = pk(s3.a.y, s3.b.y);
                    ag[4 * jb] = pk(s1.a.x, s1.b.x); ag[4 * jb + 1] = pk(s2.a.x, s2.b.x); ag[4 * jb + 2] = pk(s1.a.y, s1.b.y); ag[4 * jb + 3] = pk(s2.a.y, s2.b.y);
                }
                pinu(af);
                pinu(ag);
                warp_arrive(bars + B_WFREE);
                wg_fence();
#pragma unroll
                for (int j = 0; j < 4; j++) mma64_rs<1>(ya, af[4 * j], af[4 * j + 1], af[4 * j + 2], af[4 * j + 3], dF + j * 128, j);
                wg_commit();
#pragma unroll
                for (int j = 0; j < 4; j++) mma64_rs<1>(yb, ag[4 * j], ag[4 * j + 1], ag[4 * j + 2], ag[4 * j + 3], dF + j * 128, j);
                wg_commit();
                STAMP3(33);
                {
                    const uint32_t a0 = buf + (mi & 1) * 4096 + (16 * w + 8 * (mi >> 1) + gl) * 64 + ((gl >> 1) << 4);
#pragma unroll
                    for (int h = 0; h < 2; h++) {
                        if (h == 0) { wg_wait<1>(); pin(ya); pinu(af); STAMP3(34); } else { wg_wait<0>(); pin(yb); pinu(ag); }
                        const float(&yy)[32] = h ? yb : ya;
#pragma unroll
                        for (int c = 0; c < 4; c++) {
                            const int i = 8 * ((c + 2 * h) & 3), k = 8 * ((c + 2 * h + 1) & 3) + 2;
                            c2 x = {cmulc({yy[i], yy[i + 1]}, T[2 * c]), cmulc({yy[k], yy[k + 1]}, T[2 * c])};
                            fin<1>(x);
                            c2 y = {cmulc({yy[i + 4], yy[i + 5]}, T[2 * c + 1]), cmulc({yy[k + 4], yy[k + 5]}, T[2 * c + 1])};
                            fin<1>(y);
                            stsm4((a0 ^ (c << 4)) + h * 8192, pk(x.a.x, y.a.x), pk(x.b.x, y.b.x), pk(x.a.y, y.a.y), pk(x.b.y, y.b.y));
                        }
                    }
                }
                STAMP3(38);
                fence_async_sm();
                bar_sync(3, 128);
                wg_fence();
#pragma unroll
                for (int j = 0; j < 4; j++) mma128_ss<0, 1, 1>(vv, dF + j * 128, dB + j * 64, j);
                wg_commit();
                STAMP3(35);
                const int lane = fresh_lane(), g = lane >> 2, q = lane & 3;
                vp = padd(g_X + (4 << 20) + w * (8 * 32768) + (role ? u : 1) * 16384 + slot * 64,
                                         (g >> 1) * 32768 + (role ? g & 1 : u) * 32 + (((q ^ (slot >> 1)) & 1) << 4) + (q >> 1) * 8);
                const uint32_t tmask = (((g & 1) == ((slot >> 3) & 1) || !role) && q == ((slot >> 1) & 2)) ? ~1u : ~0u, tbit = (ep ^ (role + u ? 0 : g)) & ~tmask;
                be1 = twid(kap1 + 512 * q, 2048); be2 = csq(be1); be3 = cmul(be1, be2);
                asm volatile("pmevent 1;" : "+f"(be1.x), "+f"(be1.y), "+f"(be2.x), "+f"(be2.y), "+f"(be3.x), "+f"(be3.y), "+l"(vp)::"memory");
                wg_wait<0>();
                pin(vv);
                STAMP3(36);
#pragma unroll
                for (int k = 0; k < 16; k++) {
                    const int i = 8 * (k >> 1) + 2 * (k & 1);
                    vo[2 * k] = (pk(vv[i], vv[i + 1]) & tmask) | tbit;
                    vo[2 * k + 1] = pk(vv[i + 4], vv[i + 5]);
                }
                pinu(vo);
            }
            if (!role) mbar_wait(bars + B_IN + 16, 0);
            warp_arrive(bars + B_STG);
            const bool odd = fresh_lane() & 4;
            store_v<0, 4>(vo, vp, role || !odd);
            asm volatile("@p0 red.relaxed.gpu.global.add.u32 [%0], 1;" ::"l"(g_cnt + 32 + nu * 32) : "memory");
            store_v<4, 16>(vo, vp, role || odd);
            if (!spare) bar_arrive(9, 256);
        }
        if (spare) return;
        }
        {
            constexpr int Y = YP3;
            uint32_t sp[8];
            cf tw[8];
            ldtab<2, 2048>(sp, TAB_SP + fb * 4096 + t7 * 16);
            ldtab_cf<16>(tw, TAB_TW3 + fb * 2048 + (t7 >> 2) * 64);
            const uint64_t dF = opaque(mkdesc(sb + OFF_F, 16, 1024, 1)), dB = opaque(mkdesc(sb + OFF_P + hf * 8192, 1024, 256, 3));
            const uint8_t* op = padd(p.out + (1024 + fb) * 2048 + fcb * 32 + hf * 16, (t7 >> 2) * 32768 + (q >> 1) * 16 + (q & 1) * 32);
            float acc[64], out[64];
            mbar_wait(bars + B_IN + 24, 0);
            mbar_wait(bars + B_FG, 1);
            STAMP(25);
            pinu(sp);
            wg_fence();
#pragma unroll
            for (int j = 0; j < 4; j++) {
                const uint64_t db = dB + (j >> 1) * 1024 + (j & 1) * 32;
                mma112_ss(acc, dF + j * 2, db + 64, j);
                if (j & 1) mma16_rs(acc, 0u, sp[2 * j], 0u, sp[2 * j + 1], db, 1);
                else mma16_rs(acc, sp[2 * j], 0u, sp[2 * j + 1], 0u, db, j);
            }
            wg_commit();
            wg_wait<0>();
            pin(acc);
            pinu(sp);
            warp_arrive(bars + B_P3M);
            if (!hf) bar_sync(5, 256);
#pragma unroll
            for (int cl = 0; cl < 2; cl++) {
                c2 z[8];
#pragma unroll
                for (int n = 0; n < 8; n++) {
                    const int i = 4 * (2 * n + cl);
                    z[n] = {{acc[i], acc[i + 2]}, {acc[i + 1], acc[i + 3]}};
                }
                z[0] = {{z[0].a.x + z[0].a.y, z[0].a.x - z[0].a.y}, {z[0].b.x + z[0].b.y, z[0].b.x - z[0].b.y}};
                z[4] = mul2(z[4], tw[4]);
                fin<Y>(z[0], z[4]);
#pragma unroll
                for (int n = 1; n < 4; n++) {
                    const cf iw = n == 1 ? cf{0.38268343236508977f, 0.92387953251128674f}
                                         : (n == 2 ? cf{0.70710678118654752f, 0.70710678118654752f} : cf{0.92387953251128674f, 0.38268343236508977f});
                    c2 y = mul2(z[n], tw[n]);
                    fin<Y>(y);
                    const cf t = {tw[8 - n].x, -tw[8 - n].y};
                    c2 E = fma2(c2{{z[8 - n].a.x, -z[8 - n].a.y}, {z[8 - n].b.x, -z[8 - n].b.y}}, t, y);
                    fin<Y>(E);
                    z[n] = fma2(twm2(y, E), iw, E);
                    fin<Y>(z[n]);
                    z[8 - n] = {{fmaf(2.f, E.a.x, -z[n].a.x), fmaf(-2.f, E.a.y, z[n].a.y)}, {fmaf(2.f, E.b.x, -z[n].b.x), fmaf(-2.f, E.b.y, z[n].b.y)}};
                }
                dft8<false, Y>(z, tw);
#pragma unroll
                for (int m = 0; m < 8; m++) {
                    out[8 * m + 2 * cl] = z[m].a.x; out[8 * m + 2 * cl + 1] = z[m].b.x;
                    out[8 * m + 4 + 2 * cl] = z[m].a.y; out[8 * m + 5 + 2 * cl] = z[m].b.y;
                }
            }
            pin(out);
            if (hf) bar_arrive(5, 256);
            if (hf) STAMP(26);
#pragma unroll
            for (int m = 0; m < 16; m++) {
                asm volatile("st.global.v4.f32 [%0], {%1,%2,%3,%4};" ::"l"(op + (m - 8) * (1 << 20)), "f"(out[4 * m]), "f"(out[4 * m + 1]), "f"(out[4 * m + 2]), "f"(out[4 * m + 3]) : "memory");
                if (PACE_O && m < 15 && m % PACE_ON == PACE_ON - 1)
                    asm volatile("{.reg .pred p; mbarrier.test_wait.parity.shared::cta.b64 p, [%0], 0; @!p nanosleep.u32 %1;}" ::"r"(bars + B_DONE), "n"(PACE_O) : "memory");
            }
            STAMP(27);
        }
    }
}

typedef CUresult (*EncodeFn)(CUtensorMap*, CUtensorMapDataType, cuuint32_t, void*, const cuuint64_t*, const cuuint64_t*, const cuuint32_t*,
                             const cuuint32_t*, CUtensorMapInterleave, CUtensorMapSwizzle, CUtensorMapL2promotion, CUtensorMapFloatOOBfill);

static CUtensorMap make_map(EncodeFn enc, const void* ptr, int rank, const cuuint64_t* dims, const cuuint64_t* strides, const cuuint32_t* box,
                            CUtensorMapSwizzle swz, CUtensorMapL2promotion promo, CUtensorMapDataType dt = CU_TENSOR_MAP_DATA_TYPE_BFLOAT16) {
    CUtensorMap m;
    const cuuint32_t es[5] = {1, 1, 1, 1, 1};
    enc(&m, dt, rank, const_cast<void*>(ptr), dims, strides, box, es, CU_TENSOR_MAP_INTERLEAVE_NONE, swz, promo,
        CU_TENSOR_MAP_FLOAT_OOB_FILL_NONE);
    return m;
}

extern "C" void kernel_launch(void* const* d_in, const int* in_sizes, int n_in, void* d_out, int out_size) {
    void* fn = nullptr;
    cudaDriverEntryPointQueryResult qr;
    cudaGetDriverEntryPoint("cuTensorMapEncodeTiled", &fn, cudaEnableDefault, &qr);
    EncodeFn enc = (EncodeFn)fn;
    void* pX;
    cudaGetSymbolAddress(&pX, g_X);
    const CUtensorMapL2promotion P256 = CU_TENSOR_MAP_L2_PROMOTION_L2_256B, P0 = CU_TENSOR_MAP_L2_PROMOTION_NONE;

    const cuuint64_t dX[5] = {1024, 2, 4, 16, 16}, sX[4] = {2048, 32 * 2048, 2 * 2048, 128 * 2048};
    const cuuint32_t bX[5] = {64, 2, 4, 16, 1};
    CUtensorMap tmX = make_map(enc, d_in[3], 5, dX, sX, bX, CU_TENSOR_MAP_SWIZZLE_128B, P256);
    const cuuint64_t dXd[4] = {64, 2048, 2, 16}, sXd[3] = {2048, 64 * 2048, 128};
    const cuuint32_t bXd[4] = {64, 16, 2, 2};
    CUtensorMap tmXd = make_map(enc, d_in[3], 4, dXd, sXd, bXd, CU_TENSOR_MAP_SWIZZLE_128B, P256);
    const cuuint64_t dB[4] = {1024, 8, 4, 32}, sB[3] = {2048, 256 * 2048, 8 * 2048};
    const cuuint32_t bB4[4] = {64, 8, 2, 4};
    CUtensorMap tmBre = make_map(enc, d_in[6], 4, dB, sB, bB4, CU_TENSOR_MAP_SWIZZLE_128B, P256);
    CUtensorMap tmBim = make_map(enc, d_in[7], 4, dB, sB, bB4, CU_TENSOR_MAP_SWIZZLE_128B, P256);
    const cuuint64_t dC[5] = {1024, 2, 4, 2, 64}, sC[4] = {2048, 4 * 2048, 2 * 2048, 16 * 2048};
    const cuuint32_t bC[5] = {64, 2, 4, 2, 4};
    CUtensorMap tmCre = make_map(enc, d_in[8], 5, dC, sC, bC, CU_TENSOR_MAP_SWIZZLE_128B, P256);
    CUtensorMap tmCim = make_map(enc, d_in[9], 5, dC, sC, bC, CU_TENSOR_MAP_SWIZZLE_128B, P256);

    const cuuint64_t dU[2] = {8192, 256}, sU[1] = {16384};
    const cuuint32_t bU[2] = {64, 64};
    CUtensorMap tmUst = make_map(enc, pX, 2, dU, sU, bU, CU_TENSOR_MAP_SWIZZLE_128B, P0);
    const cuuint64_t dV[2] = {16384, 128}, sV[1] = {32768};
    const cuuint32_t bV[2] = {32, 128};
    CUtensorMap tmVst = make_map(enc, (uint8_t*)pX + (4 << 20), 2, dV, sV, bV, CU_TENSOR_MAP_SWIZZLE_NONE, P0);
    const cuuint64_t dF[2] = {512 * 1026 / 8, 4}, sF[1] = {512 * 1026};
    const cuuint32_t bF[2] = {WPITCH / 8, 4};
    CUtensorMap tmWr = make_map(enc, d_in[1], 2, dF, sF, bF, CU_TENSOR_MAP_SWIZZLE_NONE, P0, CU_TENSOR_MAP_DATA_TYPE_UINT64);
    CUtensorMap tmWi = make_map(enc, d_in[2], 2, dF, sF, bF, CU_TENSOR_MAP_SWIZZLE_NONE, P0, CU_TENSOR_MAP_DATA_TYPE_UINT64);

    const cuuint64_t dA[3] = {1024, 64, 32}, sA[2] = {32 * 2048, 2048};
    const cuuint32_t bA[3] = {32, 64, 1};
    CUtensorMap tmXa = make_map(enc, d_in[0], 3, dA, sA, bA, CU_TENSOR_MAP_SWIZZLE_64B, CU_TENSOR_MAP_L2_PROMOTION_L2_128B);

    Params p;
    p.wr = (const __nv_bfloat16*)d_in[1];
    p.wi = (const __nv_bfloat16*)d_in[2];
    p.lre = (const __nv_bfloat16*)d_in[4];
    p.lim = (const __nv_bfloat16*)d_in[5];
    p.ldt = (const __nv_bfloat16*)d_in[10];
    p.dsk = (const __nv_bfloat16*)d_in[11];
    p.out = (float*)d_out;
    int dev = 0, sms = 0;
    cudaGetDevice(&dev);
    cudaDeviceGetAttribute(&sms, cudaDevAttrMultiProcessorCount, dev);
    auto kernel = sms == 132 ? fused_kernel<true> : fused_kernel<false>;
    cudaFuncSetAttribute(kernel, cudaFuncAttributeMaxDynamicSharedMemorySize, SMEM_BYTES);
    kernel<<<132, 512, SMEM_BYTES>>>(tmX, tmBre, tmBim, tmCre, tmCim, tmXd, tmUst, tmVst, tmWr, tmWi, tmXa, p);
}
```

```cpp
#include <cuda_runtime.h>
#include <cuda.h>
#include <cuda_bf16.h>
#include <stdint.h>

#define NST 5
#define WPITCH 1056
#define OFF_P (NST * 32768)
#define OFF_F (OFF_P + 32768)
#define OFF_WD (OFF_F + 8192)
#define OFF_WM (OFF_WD + 8 * WPITCH)
#define OFF_BAR (OFF_F + 32768)
#define OFF_LAM (OFF_BAR + 432)
#define OFF_WSP (OFF_LAM + 2048)
#define OFF_PROF (OFF_WSP + 128)
#define SMEM_BYTES OFF_PROF
#define B_FULL 0
#define B_HL 40
#define B_EP 120
#define B_HR 128
#define B_XD 144
#define B_FG 160
#define B_WSP 168
#define B_WD 176
#define B_DONE 184
#define B_LD 192
#define B_RAW 200
#define B_LAM 208
#define B_IN 216
#define B_XIN 248
#define B_EMPTY 256
#define B_STG 320
#define B_WFREE 328
#define B_HOWN 336
#define B_STGU 368
#define B_P3M 384
#define B_EPOCH 416

#define XA_PACE 200
#define PACE_O 200
#define PACE_ON 2
#define TAB_T0 500
#define LAM_T0 1000
#define XA_N0 2
#define PACE_X 200
#define SKEW 4
#define SPIN_LIMIT (1u << 15)

__device__ __align__(1024) uint8_t g_X[8 << 20];
__device__ __align__(1024) uint8_t g_H[8 << 20];
__device__ __align__(1024) uint4 g_carry[16 * 512];
__device__ __align__(128) unsigned g_cnt[128];
__device__ __align__(128) unsigned g_epoch[132 * 8];

#define STAMP(i) do { } while (0)
#define STAMPO(i, o) do { } while (0)
#define STAMPW(a, b) do { } while (0)
#define STAMPX(a, b) do { } while (0)
#define STAMP5(i) do { } while (0)
#define STAMP3(i) do { } while (0)

#define TAB_FG 0
#define TAB_G 8192
#define TAB_F1 40960
#define TAB_T 49152
#define TAB_SP 57344
#define TAB_TW1 73728
#define TAB_TW3 75776
#define TAB_PC 83968
__device__ __align__(1024) const uint32_t g_tab[21248] = {
0x80003d80,0x80003d80,0x80003d80,0x80003d80,0x80003d80,0x80003d80,0x80003d80,0x80003d80,0x80003d80,0x80003d80,0x80003d80,0x80003d80,0x80003d80,0x80003d80,0x80003d80,0x80003d80,
0x80003d80,0x80003d80,0x80003d80,0x80003d80,0x80003d80,0x80003d80,0x80003d80,0x80003d80,0x80003d80,0x80003d80,0x80003d80,0x80003d80,0x80003d80,0x80003d80,0x80003d80,0x80003d80,
0x3d353d35,0x3d35bd35,0xbd35bd35,0xbd353d35,0x80003d80,0x3d800000,0x8000bd80,0xbd800000,0x3d353d35,0x3d35bd35,0xbd35bd35,0xbd353d35,0x80003d80,0x3d800000,0x8000bd80,0xbd800000,
0x3d353d35,0x3d35bd35,0xbd35bd35,0xbd353d35,0x80003d80,0x3d800000,0x8000bd80,0xbd800000,0x3d353d35,0x3d35bd35,0xbd35bd35,0xbd353d35,0x80003d80,0x3d800000,0x8000bd80,0xbd800000,
0x3d800000,0x3d6dbcc4,0x3d35bd35,0x3cc4bd6d,0x3d7bbc48,0x3d55bd0e,0x3d0ebd55,0x3c48bd7b,0x80003d80,0x3cc43d6d,0x3d353d35,0x3d6d3cc4,0x3c483d7b,0x3d0e3d55,0x3d553d0e,0x3d7b3c48,
0xbd800000,0xbd6d3cc4,0xbd353d35,0xbcc43d6d,0xbd7b3c48,0xbd553d0e,0xbd0e3d55,0xbc483d7b,0x8000bd80,0xbcc4bd6d,0xbd35bd35,0xbd6dbcc4,0xbc48bd7b,0xbd0ebd55,0xbd55bd0e,0xbd7bbc48,
0x3d0ebd55,0xbd7bbc48,0x3c483d7b,0x3d55bd0e,0x3d800000,0xbcc4bd6d,0xbd353d35,0x3d6d3cc4,0x3d553d0e,0x3c48bd7b,0xbd7b3c48,0x3d0e3d55,0x80003d80,0x3d6dbcc4,0xbd35bd35,0xbcc43d6d,
0xbd0e3d55,0x3d7b3c48,0xbc48bd7b,0xbd553d0e,0xbd800000,0x3cc43d6d,0x3d35bd35,0xbd6dbcc4,0xbd55bd0e,0xbc483d7b,0x3d7bbc48,0xbd0ebd55,0x8000bd80,0xbd6d3cc4,0x3d353d35,0x3cc4bd6d,
0x80003d80,0x3d353d35,0x3d800000,0x3d35bd35,0x3cc43d6d,0x3d6d3cc4,0x3d6dbcc4,0x3cc4bd6d,0x8000bd80,0xbd35bd35,0xbd800000,0xbd353d35,0xbcc4bd6d,0xbd6dbcc4,0xbd6d3cc4,0xbcc43d6d,
0x80003d80,0x3d353d35,0x3d800000,0x3d35bd35,0x3cc43d6d,0x3d6d3cc4,0x3d6dbcc4,0x3cc4bd6d,0x8000bd80,0xbd35bd35,0xbd800000,0xbd353d35,0xbcc4bd6d,0xbd6dbcc4,0xbd6d3cc4,0xbcc43d6d,
0x3d6d3cc4,0xbcc4bd6d,0xbcc43d6d,0x3d6dbcc4,0x80003d80,0x3d35bd35,0xbd800000,0x3d353d35,0xbd6dbcc4,0x3cc43d6d,0x3cc4bd6d,0xbd6d3cc4,0x8000bd80,0xbd353d35,0x3d800000,0xbd35bd35,
0x3d6d3cc4,0xbcc4bd6d,0xbcc43d6d,0x3d6dbcc4,0x80003d80,0x3d35bd35,0xbd800000,0x3d353d35,0xbd6dbcc4,0x3cc43d6d,0x3cc4bd6d,0xbd6d3cc4,0x8000bd80,0xbd353d35,0x3d800000,0xbd35bd35,
0x3d800000,0x3cc4bd6d,0xbd35bd35,0xbd6d3cc4,0x3d55bd0e,0xbc48bd7b,0xbd7bbc48,0xbd0e3d55,0x8000bd80,0xbd6dbcc4,0xbd353d35,0x3cc43d6d,0xbd0ebd55,0xbd7b3c48,0xbc483d7b,0x3d553d0e,
0xbd800000,0xbcc43d6d,0x3d353d35,0x3d6dbcc4,0xbd553d0e,0x3c483d7b,0x3d7b3c48,0x3d0ebd55,0x80003d80,0x3d6d3cc4,0x3d35bd35,0xbcc4bd6d,0x3d0e3d55,0x3d7bbc48,0x3c48bd7b,0xbd55bd0e,
0x3c48bd7b,0xbd0e3d55,0x3d55bd0e,0xbd7b3c48,0x3d800000,0xbd6dbcc4,0x3d353d35,0xbcc4bd6d,0xbd7bbc48,0x3d553d0e,0xbd0ebd55,0x3c483d7b,0x8000bd80,0xbcc43d6d,0x3d35bd35,0xbd6d3cc4,
0xbc483d7b,0x3d0ebd55,0xbd553d0e,0x3d7bbc48,0xbd800000,0x3d6d3cc4,0xbd35bd35,0x3cc43d6d,0x3d7b3c48,0xbd55bd0e,0x3d0e3d55,0xbc48bd7b,0x80003d80,0x3cc4bd6d,0xbd353d35,0x3d6dbcc4,
0x3d800000,0x3d800000,0x3d800000,0x3d800000,0x3d800000,0x3d800000,0x3d800000,0x3d800000,0x3d800000,0x3d800000,0x3d800000,0x3d800000,0x3d800000,0x3d800000,0x3d800000,0x3d800000,
0x3d800000,0x3d800000,0x3d800000,0x3d800000,0x3d800000,0x3d800000,0x3d800000,0x3d800000,0x3d800000,0x3d800000,0x3d800000,0x3d800000,0x3d800000,0x3d800000,0x3d800000,0x3d800000,
0x3d35bd35,0xbd35bd35,0xbd353d35,0x3d353d35,0x3d800000,0xbd80,0xbd800000,0x3d80,0x3d35bd35,0xbd35bd35,0xbd353d35,0x3d353d35,0x3d800000,0xbd80,0xbd800000,0x3d80,
0x3d35bd35,0xbd35bd35,0xbd353d35,0x3d353d35,0x3d800000,0xbd80,0xbd800000,0x3d80,0x3d35bd35,0xbd35bd35,0xbd353d35,0x3d353d35,0x3d800000,0xbd80,0xbd800000,0x3d80,
0xbd80,0xbcc4bd6d,0xbd35bd35,0xbd6dbcc4,0xbc48bd7b,0xbd0ebd55,0xbd55bd0e,0xbd7bbc48,0x3d800000,0x3d6dbcc4,0x3d35bd35,0x3cc4bd6d,0x3d7bbc48,0x3d55bd0e,0x3d0ebd55,0x3c48bd7b,
0x3d80,0x3cc43d6d,0x3d353d35,0x3d6d3cc4,0x3c483d7b,0x3d0e3d55,0x3d553d0e,0x3d7b3c48,0xbd800000,0xbd6d3cc4,0xbd353d35,0xbcc43d6d,0xbd7b3c48,0xbd553d0e,0xbd0e3d55,0xbc483d7b,
0xbd55bd0e,0xbc483d7b,0x3d7bbc48,0xbd0ebd55,0xbd80,0xbd6d3cc4,0x3d353d35,0x3cc4bd6d,0x3d0ebd55,0xbd7bbc48,0x3c483d7b,0x3d55bd0e,0x3d800000,0xbcc4bd6d,0xbd353d35,0x3d6d3cc4,
0x3d553d0e,0x3c48bd7b,0xbd7b3c48,0x3d0e3d55,0x3d80,0x3d6dbcc4,0xbd35bd35,0xbcc43d6d,0xbd0e3d55,0x3d7b3c48,0xbc48bd7b,0xbd553d0e,0xbd800000,0x3cc43d6d,0x3d35bd35,0xbd6dbcc4,
0x3d800000,0x3d35bd35,0xbd80,0xbd35bd35,0x3d6dbcc4,0x3cc4bd6d,0xbcc4bd6d,0xbd6dbcc4,0xbd800000,0xbd353d35,0x3d80,0x3d353d35,0xbd6d3cc4,0xbcc43d6d,0x3cc43d6d,0x3d6d3cc4,
0x3d800000,0x3d35bd35,0xbd80,0xbd35bd35,0x3d6dbcc4,0x3cc4bd6d,0xbcc4bd6d,0xbd6dbcc4,0xbd800000,0xbd353d35,0x3d80,0x3d353d35,0xbd6d3cc4,0xbcc43d6d,0x3cc43d6d,0x3d6d3cc4,
0x3cc4bd6d,0xbd6d3cc4,0x3d6d3cc4,0xbcc4bd6d,0x3d800000,0xbd35bd35,0x3d80,0x3d35bd35,0xbcc43d6d,0x3d6dbcc4,0xbd6dbcc4,0x3cc43d6d,0xbd800000,0x3d353d35,0xbd80,0xbd353d35,
0x3cc4bd6d,0xbd6d3cc4,0x3d6d3cc4,0xbcc4bd6d,0x3d800000,0xbd35bd35,0x3d80,0x3d35bd35,0xbcc43d6d,0x3d6dbcc4,0xbd6dbcc4,0x3cc43d6d,0xbd800000,0x3d353d35,0xbd80,0xbd353d35,
0xbd80,0xbd6dbcc4,0xbd353d35,0x3cc43d6d,0xbd0ebd55,0xbd7b3c48,0xbc483d7b,0x3d553d0e,0xbd800000,0xbcc43d6d,0x3d353d35,0x3d6dbcc4,0xbd553d0e,0x3c483d7b,0x3d7b3c48,0x3d0ebd55,
0x3d80,0x3d6d3cc4,0x3d35bd35,0xbcc4bd6d,0x3d0e3d55,0x3d7bbc48,0x3c48bd7b,0xbd55bd0e,0x3d800000,0x3cc4bd6d,0xbd35bd35,0xbd6d3cc4,0x3d55bd0e,0xbc48bd7b,0xbd7bbc48,0xbd0e3d55,
0xbd7bbc48,0x3d553d0e,0xbd0ebd55,0x3c483d7b,0xbd80,0xbcc43d6d,0x3d35bd35,0xbd6d3cc4,0xbc483d7b,0x3d0ebd55,0xbd553d0e,0x3d7bbc48,0xbd800000,0x3d6d3cc4,0xbd35bd35,0x3cc43d6d,
0x3d7b3c48,0xbd55bd0e,0x3d0e3d55,0xbc48bd7b,0x3d80,0x3cc4bd6d,0xbd353d35,0x3d6dbcc4,0x3c48bd7b,0xbd0e3d55,0x3d55bd0e,0xbd7b3c48,0x3d800000,0xbd6dbcc4,0x3d353d35,0xbcc4bd6d,
0x80003d80,0x8000bd80,0x80003d80,0x8000bd80,0x3d800000,0xbd800000,0x3d800000,0xbd800000,0x80003d80,0x8000bd80,0x80003d80,0x8000bd80,0x3d800000,0xbd800000,0x3d800000,0xbd800000,
0x80003d80,0x8000bd80,0x80003d80,0x8000bd80,0x3d800000,0xbd800000,0x3d800000,0xbd800000,0x80003d80,0x8000bd80,0x80003d80,0x8000bd80,0x3d800000,0xbd800000,0x3d800000,0xbd800000,
0x3d35bd35,0x3d353d35,0xbd353d35,0xbd35bd35,0x80003d80,0xbd800000,0x8000bd80,0x3d800000,0x3d35bd35,0x3d353d35,0xbd353d35,0xbd35bd35,0x80003d80,0xbd800000,0x8000bd80,0x3d800000,
0x3d35bd35,0x3d353d35,0xbd353d35,0xbd35bd35,0x80003d80,0xbd800000,0x8000bd80,0x3d800000,0x3d35bd35,0x3d353d35,0xbd353d35,0xbd35bd35,0x80003d80,0xbd800000,0x8000bd80,0x3d800000,
0x3d800000,0xbd6d3cc4,0x3d35bd35,0xbcc43d6d,0xbc48bd7b,0x3d0e3d55,0xbd55bd0e,0x3d7b3c48,0x80003d80,0xbcc4bd6d,0x3d353d35,0xbd6dbcc4,0x3d7bbc48,0xbd553d0e,0x3d0ebd55,0xbc483d7b,
0xbd800000,0x3d6dbcc4,0xbd353d35,0x3cc4bd6d,0x3c483d7b,0xbd0ebd55,0x3d553d0e,0xbd7bbc48,0x8000bd80,0x3cc43d6d,0xbd35bd35,0x3d6d3cc4,0xbd7b3c48,0x3d55bd0e,0xbd0e3d55,0x3c48bd7b,
0xbd55bd0e,0x3c48bd7b,0x3d7bbc48,0x3d0e3d55,0x3d800000,0x3cc43d6d,0xbd353d35,0xbd6dbcc4,0x3d0ebd55,0x3d7b3c48,0x3c483d7b,0xbd553d0e,0x80003d80,0xbd6d3cc4,0xbd35bd35,0x3cc4bd6d,
0x3d553d0e,0xbc483d7b,0xbd7b3c48,0xbd0ebd55,0xbd800000,0xbcc4bd6d,0x3d35bd35,0x3d6d3cc4,0xbd0e3d55,0xbd7bbc48,0xbc48bd7b,0x3d55bd0e,0x8000bd80,0x3d6dbcc4,0x3d353d35,0xbcc43d6d,
0x80003d80,0xbd35bd35,0x3d800000,0xbd353d35,0x3d6dbcc4,0xbcc43d6d,0xbcc4bd6d,0x3d6d3cc4,0x8000bd80,0x3d353d35,0xbd800000,0x3d35bd35,0xbd6d3cc4,0x3cc4bd6d,0x3cc43d6d,0xbd6dbcc4,
0x80003d80,0xbd35bd35,0x3d800000,0xbd353d35,0x3d6dbcc4,0xbcc43d6d,0xbcc4bd6d,0x3d6d3cc4,0x8000bd80,0x3d353d35,0xbd800000,0x3d35bd35,0xbd6d3cc4,0x3cc4bd6d,0x3cc43d6d,0xbd6dbcc4,
0x3cc4bd6d,0x3d6dbcc4,0x3d6d3cc4,0x3cc43d6d,0x80003d80,0xbd353d35,0xbd800000,0xbd35bd35,0xbcc43d6d,0xbd6d3cc4,0xbd6dbcc4,0xbcc4bd6d,0x8000bd80,0x3d35bd35,0x3d800000,0x3d353d35,
0x3cc4bd6d,0x3d6dbcc4,0x3d6d3cc4,0x3cc43d6d,0x80003d80,0xbd353d35,0xbd800000,0xbd35bd35,0xbcc43d6d,0xbd6d3cc4,0xbd6dbcc4,0xbcc4bd6d,0x8000bd80,0x3d35bd35,0x3d800000,0x3d353d35,
0x3d800000,0xbcc43d6d,0xbd35bd35,0x3d6dbcc4,0xbd0ebd55,0x3d7bbc48,0xbc483d7b,0xbd55bd0e,0x8000bd80,0x3d6d3cc4,0xbd353d35,0xbcc4bd6d,0xbd553d0e,0xbc48bd7b,0x3d7b3c48,0xbd0e3d55,
0xbd800000,0x3cc4bd6d,0x3d353d35,0xbd6d3cc4,0x3d0e3d55,0xbd7b3c48,0x3c48bd7b,0x3d553d0e,0x80003d80,0xbd6dbcc4,0x3d35bd35,0x3cc43d6d,0x3d55bd0e,0x3c483d7b,0xbd7bbc48,0x3d0ebd55,
0xbd7bbc48,0xbd55bd0e,0xbd0ebd55,0xbc48bd7b,0x3d800000,0x3d6d3cc4,0x3d353d35,0x3cc43d6d,0xbc483d7b,0xbd0e3d55,0xbd553d0e,0xbd7b3c48,0x8000bd80,0x3cc4bd6d,0x3d35bd35,0x3d6dbcc4,
0x3d7b3c48,0x3d553d0e,0x3d0e3d55,0x3c483d7b,0xbd800000,0xbd6dbcc4,0xbd35bd35,0xbcc4bd6d,0x3c48bd7b,0x3d0ebd55,0x3d55bd0e,0x3d7bbc48,0x80003d80,0xbcc43d6d,0xbd353d35,0xbd6d3cc4,
0x3d800000,0xbd800000,0x3d800000,0xbd800000,0xbd80,0x3d80,0xbd80,0x3d80,0x3d800000,0xbd800000,0x3d800000,0xbd800000,0xbd80,0x3d80,0xbd80,0x3d80,
0x3d800000,0xbd800000,0x3d800000,0xbd800000,0xbd80,0x3d80,0xbd80,0x3d80,0x3d800000,0xbd800000,0x3d800000,0xbd800000,0xbd80,0x3d80,0xbd80,0x3d80,
0xbd35bd35,0x3d35bd35,0x3d353d35,0xbd353d35,0x3d800000,0x3d80,0xbd800000,0xbd80,0xbd35bd35,0x3d35bd35,0x3d353d35,0xbd353d35,0x3d800000,0x3d80,0xbd800000,0xbd80,
0xbd35bd35,0x3d35bd35,0x3d353d35,0xbd353d35,0x3d800000,0x3d80,0xbd800000,0xbd80,0xbd35bd35,0x3d35bd35,0x3d353d35,0xbd353d35,0x3d800000,0x3d80,0xbd800000,0xbd80,
0xbd80,0x3cc43d6d,0xbd35bd35,0x3d6d3cc4,0xbd7b3c48,0x3d55bd0e,0xbd0e3d55,0x3c48bd7b,0x3d800000,0xbd6d3cc4,0x3d35bd35,0xbcc43d6d,0xbc48bd7b,0x3d0e3d55,0xbd55bd0e,0x3d7b3c48,
0x3d80,0xbcc4bd6d,0x3d353d35,0xbd6dbcc4,0x3d7bbc48,0xbd553d0e,0x3d0ebd55,0xbc483d7b,0xbd800000,0x3d6dbcc4,0xbd353d35,0x3cc4bd6d,0x3c483d7b,0xbd0ebd55,0x3d553d0e,0xbd7bbc48,
0xbd0e3d55,0xbd7bbc48,0xbc48bd7b,0x3d55bd0e,0xbd80,0x3d6dbcc4,0x3d353d35,0xbcc43d6d,0xbd55bd0e,0x3c48bd7b,0x3d7bbc48,0x3d0e3d55,0x3d800000,0x3cc43d6d,0xbd353d35,0xbd6dbcc4,
0x3d0ebd55,0x3d7b3c48,0x3c483d7b,0xbd553d0e,0x3d80,0xbd6d3cc4,0xbd35bd35,0x3cc4bd6d,0x3d553d0e,0xbc483d7b,0xbd7b3c48,0xbd0ebd55,0xbd800000,0xbcc4bd6d,0x3d35bd35,0x3d6d3cc4,
0x3d800000,0xbd353d35,0xbd80,0x3d353d35,0xbcc4bd6d,0x3d6d3cc4,0xbd6d3cc4,0x3cc4bd6d,0xbd800000,0x3d35bd35,0x3d80,0xbd35bd35,0x3cc43d6d,0xbd6dbcc4,0x3d6dbcc4,0xbcc43d6d,
0x3d800000,0xbd353d35,0xbd80,0x3d353d35,0xbcc4bd6d,0x3d6d3cc4,0xbd6d3cc4,0x3cc4bd6d,0xbd800000,0x3d35bd35,0x3d80,0xbd35bd35,0x3cc43d6d,0xbd6dbcc4,0x3d6dbcc4,0xbcc43d6d,
0xbd6dbcc4,0xbcc4bd6d,0x3cc4bd6d,0x3d6dbcc4,0x3d800000,0x3d353d35,0x3d80,0xbd353d35,0x3d6d3cc4,0x3cc43d6d,0xbcc43d6d,0xbd6d3cc4,0xbd800000,0xbd35bd35,0xbd80,0x3d35bd35,
0xbd6dbcc4,0xbcc4bd6d,0x3cc4bd6d,0x3d6dbcc4,0x3d800000,0x3d353d35,0x3d80,0xbd353d35,0x3d6d3cc4,0x3cc43d6d,0xbcc43d6d,0xbd6d3cc4,0xbd800000,0xbd35bd35,0xbd80,0x3d35bd35,
0xbd80,0x3d6d3cc4,0xbd353d35,0xbcc4bd6d,0xbd553d0e,0xbc48bd7b,0x3d7b3c48,0xbd0e3d55,0xbd800000,0x3cc4bd6d,0x3d353d35,0xbd6d3cc4,0x3d0e3d55,0xbd7b3c48,0x3c48bd7b,0x3d553d0e,
0x3d80,0xbd6dbcc4,0x3d35bd35,0x3cc43d6d,0x3d55bd0e,0x3c483d7b,0xbd7bbc48,0x3d0ebd55,0x3d800000,0xbcc43d6d,0xbd35bd35,0x3d6dbcc4,0xbd0ebd55,0x3d7bbc48,0xbc483d7b,0xbd55bd0e,
0xbc483d7b,0xbd0e3d55,0xbd553d0e,0xbd7b3c48,0xbd80,0x3cc4bd6d,0x3d35bd35,0x3d6dbcc4,0x3d7b3c48,0x3d553d0e,0x3d0e3d55,0x3c483d7b,0xbd800000,0xbd6dbcc4,0xbd35bd35,0xbcc4bd6d,
0x3c48bd7b,0x3d0ebd55,0x3d55bd0e,0x3d7bbc48,0x3d80,0xbcc43d6d,0xbd353d35,0xbd6d3cc4,0xbd7bbc48,0xbd55bd0e,0xbd0ebd55,0xbc48bd7b,0x3d800000,0x3d6d3cc4,0x3d353d35,0x3cc43d6d,
0x80003d80,0x80003d80,0x80003d80,0x80003d80,0x8000bd80,0x8000bd80,0x8000bd80,0x8000bd80,0x80003d80,0x80003d80,0x80003d80,0x80003d80,0x8000bd80,0x8000bd80,0x8000bd80,0x8000bd80,
0x80003d80,0x80003d80,0x80003d80,0x80003d80,0x8000bd80,0x8000bd80,0x8000bd80,0x8000bd80,0x80003d80,0x80003d80,0x80003d80,0x80003d80,0x8000bd80,0x8000bd80,0x8000bd80,0x8000bd80,
0xbd35bd35,0xbd353d35,0x3d353d35,0x3d35bd35,0x80003d80,0x3d800000,0x8000bd80,0xbd800000,0xbd35bd35,0xbd353d35,0x3d353d35,0x3d35bd35,0x80003d80,0x3d800000,0x8000bd80,0xbd800000,
0xbd35bd35,0xbd353d35,0x3d353d35,0x3d35bd35,0x80003d80,0x3d800000,0x8000bd80,0xbd800000,0xbd35bd35,0xbd353d35,0x3d353d35,0x3d35bd35,0x80003d80,0x3d800000,0x8000bd80,0xbd800000,
0x3d800000,0x3d6dbcc4,0x3d35bd35,0x3cc4bd6d,0xbd7b3c48,0xbd553d0e,0xbd0e3d55,0xbc483d7b,0x80003d80,0x3cc43d6d,0x3d353d35,0x3d6d3cc4,0xbc48bd7b,0xbd0ebd55,0xbd55bd0e,0xbd7bbc48,
0xbd800000,0xbd6d3cc4,0xbd353d35,0xbcc43d6d,0x3d7bbc48,0x3d55bd0e,0x3d0ebd55,0x3c48bd7b,0x8000bd80,0xbcc4bd6d,0xbd35bd35,0xbd6dbcc4,0x3c483d7b,0x3d0e3d55,0x3d553d0e,0x3d7b3c48,
0xbd0e3d55,0x3d7b3c48,0xbc48bd7b,0xbd553d0e,0x3d800000,0xbcc4bd6d,0xbd353d35,0x3d6d3cc4,0xbd55bd0e,0xbc483d7b,0x3d7bbc48,0xbd0ebd55,0x80003d80,0x3d6dbcc4,0xbd35bd35,0xbcc43d6d,
0x3d0ebd55,0xbd7bbc48,0x3c483d7b,0x3d55bd0e,0xbd800000,0x3cc43d6d,0x3d35bd35,0xbd6dbcc4,0x3d553d0e,0x3c48bd7b,0xbd7b3c48,0x3d0e3d55,0x8000bd80,0xbd6d3cc4,0x3d353d35,0x3cc4bd6d,
0x80003d80,0x3d353d35,0x3d800000,0x3d35bd35,0xbcc4bd6d,0xbd6dbcc4,0xbd6d3cc4,0xbcc43d6d,0x8000bd80,0xbd35bd35,0xbd800000,0xbd353d35,0x3cc43d6d,0x3d6d3cc4,0x3d6dbcc4,0x3cc4bd6d,
0x80003d80,0x3d353d35,0x3d800000,0x3d35bd35,0xbcc4bd6d,0xbd6dbcc4,0xbd6d3cc4,0xbcc43d6d,0x8000bd80,0xbd35bd35,0xbd800000,0xbd353d35,0x3cc43d6d,0x3d6d3cc4,0x3d6dbcc4,0x3cc4bd6d,
0xbd6dbcc4,0x3cc43d6d,0x3cc4bd6d,0xbd6d3cc4,0x80003d80,0x3d35bd35,0xbd800000,0x3d353d35,0x3d6d3cc4,0xbcc4bd6d,0xbcc43d6d,0x3d6dbcc4,0x8000bd80,0xbd353d35,0x3d800000,0xbd35bd35,
0xbd6dbcc4,0x3cc43d6d,0x3cc4bd6d,0xbd6d3cc4,0x80003d80,0x3d35bd35,0xbd800000,0x3d353d35,0x3d6d3cc4,0xbcc4bd6d,0xbcc43d6d,0x3d6dbcc4,0x8000bd80,0xbd353d35,0x3d800000,0xbd35bd35,
0x3d800000,0x3cc4bd6d,0xbd35bd35,0xbd6d3cc4,0xbd553d0e,0x3c483d7b,0x3d7b3c48,0x3d0ebd55,0x8000bd80,0xbd6dbcc4,0xbd353d35,0x3cc43d6d,0x3d0e3d55,0x3d7bbc48,0x3c48bd7b,0xbd55bd0e,
0xbd800000,0xbcc43d6d,0x3d353d35,0x3d6dbcc4,0x3d55bd0e,0xbc48bd7b,0xbd7bbc48,0xbd0e3d55,0x80003d80,0x3d6d3cc4,0x3d35bd35,0xbcc4bd6d,0xbd0ebd55,0xbd7b3c48,0xbc483d7b,0x3d553d0e,
0xbc483d7b,0x3d0ebd55,0xbd553d0e,0x3d7bbc48,0x3d800000,0xbd6dbcc4,0x3d353d35,0xbcc4bd6d,0x3d7b3c48,0xbd55bd0e,0x3d0e3d55,0xbc48bd7b,0x8000bd80,0xbcc43d6d,0x3d35bd35,0xbd6d3cc4,
0x3c48bd7b,0xbd0e3d55,0x3d55bd0e,0xbd7b3c48,0xbd800000,0x3d6d3cc4,0xbd35bd35,0x3cc43d6d,0xbd7bbc48,0x3d553d0e,0xbd0ebd55,0x3c483d7b,0x80003d80,0x3cc4bd6d,0xbd353d35,0x3d6dbcc4,
0x3d800000,0x3d800000,0x3d800000,0x3d800000,0xbd800000,0xbd800000,0xbd800000,0xbd800000,0x3d800000,0x3d800000,0x3d800000,0x3d800000,0xbd800000,0xbd800000,0xbd800000,0xbd800000,
0x3d800000,0x3d800000,0x3d800000,0x3d800000,0xbd800000,0xbd800000,0xbd800000,0xbd800000,0x3d800000,0x3d800000,0x3d800000,0x3d800000,0xbd800000,0xbd800000,0xbd800000,0xbd800000,
0xbd353d35,0x3d353d35,0x3d35bd35,0xbd35bd35,0x3d800000,0xbd80,0xbd800000,0x3d80,0xbd353d35,0x3d353d35,0x3d35bd35,0xbd35bd35,0x3d800000,0xbd80,0xbd800000,0x3d80,
0xbd353d35,0x3d353d35,0x3d35bd35,0xbd35bd35,0x3d800000,0xbd80,0xbd800000,0x3d80,0xbd353d35,0x3d353d35,0x3d35bd35,0xbd35bd35,0x3d800000,0xbd80,0xbd800000,0x3d80,
0xbd80,0xbcc4bd6d,0xbd35bd35,0xbd6dbcc4,0x3c483d7b,0x3d0e3d55,0x3d553d0e,0x3d7b3c48,0x3d800000,0x3d6dbcc4,0x3d35bd35,0x3cc4bd6d,0xbd7b3c48,0xbd553d0e,0xbd0e3d55,0xbc483d7b,
0x3d80,0x3cc43d6d,0x3d353d35,0x3d6d3cc4,0xbc48bd7b,0xbd0ebd55,0xbd55bd0e,0xbd7bbc48,0xbd800000,0xbd6d3cc4,0xbd353d35,0xbcc43d6d,0x3d7bbc48,0x3d55bd0e,0x3d0ebd55,0x3c48bd7b,
0x3d553d0e,0x3c48bd7b,0xbd7b3c48,0x3d0e3d55,0xbd80,0xbd6d3cc4,0x3d353d35,0x3cc4bd6d,0xbd0e3d55,0x3d7b3c48,0xbc48bd7b,0xbd553d0e,0x3d800000,0xbcc4bd6d,0xbd353d35,0x3d6d3cc4,
0xbd55bd0e,0xbc483d7b,0x3d7bbc48,0xbd0ebd55,0x3d80,0x3d6dbcc4,0xbd35bd35,0xbcc43d6d,0x3d0ebd55,0xbd7bbc48,0x3c483d7b,0x3d55bd0e,0xbd800000,0x3cc43d6d,0x3d35bd35,0xbd6dbcc4,
0x3d800000,0x3d35bd35,0xbd80,0xbd35bd35,0xbd6d3cc4,0xbcc43d6d,0x3cc43d6d,0x3d6d3cc4,0xbd800000,0xbd353d35,0x3d80,0x3d353d35,0x3d6dbcc4,0x3cc4bd6d,0xbcc4bd6d,0xbd6dbcc4,
0x3d800000,0x3d35bd35,0xbd80,0xbd35bd35,0xbd6d3cc4,0xbcc43d6d,0x3cc43d6d,0x3d6d3cc4,0xbd800000,0xbd353d35,0x3d80,0x3d353d35,0x3d6dbcc4,0x3cc4bd6d,0xbcc4bd6d,0xbd6dbcc4,
0xbcc43d6d,0x3d6dbcc4,0xbd6dbcc4,0x3cc43d6d,0x3d800000,0xbd35bd35,0x3d80,0x3d35bd35,0x3cc4bd6d,0xbd6d3cc4,0x3d6d3cc4,0xbcc4bd6d,0xbd800000,0x3d353d35,0xbd80,0xbd353d35,
0xbcc43d6d,0x3d6dbcc4,0xbd6dbcc4,0x3cc43d6d,0x3d800000,0xbd35bd35,0x3d80,0x3d35bd35,0x3cc4bd6d,0xbd6d3cc4,0x3d6d3cc4,0xbcc4bd6d,0xbd800000,0x3d353d35,0xbd80,0xbd353d35,
0xbd80,0xbd6dbcc4,0xbd353d35,0x3cc43d6d,0x3d0e3d55,0x3d7bbc48,0x3c48bd7b,0xbd55bd0e,0xbd800000,0xbcc43d6d,0x3d353d35,0x3d6dbcc4,0x3d55bd0e,0xbc48bd7b,0xbd7bbc48,0xbd0e3d55,
0x3d80,0x3d6d3cc4,0x3d35bd35,0xbcc4bd6d,0xbd0ebd55,0xbd7b3c48,0xbc483d7b,0x3d553d0e,0x3d800000,0x3cc4bd6d,0xbd35bd35,0xbd6d3cc4,0xbd553d0e,0x3c483d7b,0x3d7b3c48,0x3d0ebd55,
0x3d7b3c48,0xbd55bd0e,0x3d0e3d55,0xbc48bd7b,0xbd80,0xbcc43d6d,0x3d35bd35,0xbd6d3cc4,0x3c48bd7b,0xbd0e3d55,0x3d55bd0e,0xbd7b3c48,0xbd800000,0x3d6d3cc4,0xbd35bd35,0x3cc43d6d,
0xbd7bbc48,0x3d553d0e,0xbd0ebd55,0x3c483d7b,0x3d80,0x3cc4bd6d,0xbd353d35,0x3d6dbcc4,0xbc483d7b,0x3d0ebd55,0xbd553d0e,0x3d7bbc48,0x3d800000,0xbd6dbcc4,0x3d353d35,0xbcc4bd6d,
0x80003d80,0x8000bd80,0x80003d80,0x8000bd80,0xbd800000,0x3d800000,0xbd800000,0x3d800000,0x80003d80,0x8000bd80,0x80003d80,0x8000bd80,0xbd800000,0x3d800000,0xbd800000,0x3d800000,
0x80003d80,0x8000bd80,0x80003d80,0x8000bd80,0xbd800000,0x3d800000,0xbd800000,0x3d800000,0x80003d80,0x8000bd80,0x80003d80,0x8000bd80,0xbd800000,0x3d800000,0xbd800000,0x3d800000,
0xbd353d35,0xbd35bd35,0x3d35bd35,0x3d353d35,0x80003d80,0xbd800000,0x8000bd80,0x3d800000,0xbd353d35,0xbd35bd35,0x3d35bd35,0x3d353d35,0x80003d80,0xbd800000,0x8000bd80,0x3d800000,
0xbd353d35,0xbd35bd35,0x3d35bd35,0x3d353d35,0x80003d80,0xbd800000,0x8000bd80,0x3d800000,0xbd353d35,0xbd35bd35,0x3d35bd35,0x3d353d35,0x80003d80,0xbd800000,0x8000bd80,0x3d800000,
0x3d800000,0xbd6d3cc4,0x3d35bd35,0xbcc43d6d,0x3c483d7b,0xbd0ebd55,0x3d553d0e,0xbd7bbc48,0x80003d80,0xbcc4bd6d,0x3d353d35,0xbd6dbcc4,0xbd7b3c48,0x3d55bd0e,0xbd0e3d55,0x3c48bd7b,
0xbd800000,0x3d6dbcc4,0xbd353d35,0x3cc4bd6d,0xbc48bd7b,0x3d0e3d55,0xbd55bd0e,0x3d7b3c48,0x8000bd80,0x3cc43d6d,0xbd35bd35,0x3d6d3cc4,0x3d7bbc48,0xbd553d0e,0x3d0ebd55,0xbc483d7b,
0x3d553d0e,0xbc483d7b,0xbd7b3c48,0xbd0ebd55,0x3d800000,0x3cc43d6d,0xbd353d35,0xbd6dbcc4,0xbd0e3d55,0xbd7bbc48,0xbc48bd7b,0x3d55bd0e,0x80003d80,0xbd6d3cc4,0xbd35bd35,0x3cc4bd6d,
0xbd55bd0e,0x3c48bd7b,0x3d7bbc48,0x3d0e3d55,0xbd800000,0xbcc4bd6d,0x3d35bd35,0x3d6d3cc4,0x3d0ebd55,0x3d7b3c48,0x3c483d7b,0xbd553d0e,0x8000bd80,0x3d6dbcc4,0x3d353d35,0xbcc43d6d,
0x80003d80,0xbd35bd35,0x3d800000,0xbd353d35,0xbd6d3cc4,0x3cc4bd6d,0x3cc43d6d,0xbd6dbcc4,0x8000bd80,0x3d353d35,0xbd800000,0x3d35bd35,0x3d6dbcc4,0xbcc43d6d,0xbcc4bd6d,0x3d6d3cc4,
0x80003d80,0xbd35bd35,0x3d800000,0xbd353d35,0xbd6d3cc4,0x3cc4bd6d,0x3cc43d6d,0xbd6dbcc4,0x8000bd80,0x3d353d35,0xbd800000,0x3d35bd35,0x3d6dbcc4,0xbcc43d6d,0xbcc4bd6d,0x3d6d3cc4,
0xbcc43d6d,0xbd6d3cc4,0xbd6dbcc4,0xbcc4bd6d,0x80003d80,0xbd353d35,0xbd800000,0xbd35bd35,0x3cc4bd6d,0x3d6dbcc4,0x3d6d3cc4,0x3cc43d6d,0x8000bd80,0x3d35bd35,0x3d800000,0x3d353d35,
0xbcc43d6d,0xbd6d3cc4,0xbd6dbcc4,0xbcc4bd6d,0x80003d80,0xbd353d35,0xbd800000,0xbd35bd35,0x3cc4bd6d,0x3d6dbcc4,0x3d6d3cc4,0x3cc43d6d,0x8000bd80,0x3d35bd35,0x3d800000,0x3d353d35,
0x3d800000,0xbcc43d6d,0xbd35bd35,0x3d6dbcc4,0x3d0e3d55,0xbd7b3c48,0x3c48bd7b,0x3d553d0e,0x8000bd80,0x3d6d3cc4,0xbd353d35,0xbcc4bd6d,0x3d55bd0e,0x3c483d7b,0xbd7bbc48,0x3d0ebd55,
0xbd800000,0x3cc4bd6d,0x3d353d35,0xbd6d3cc4,0xbd0ebd55,0x3d7bbc48,0xbc483d7b,0xbd55bd0e,0x80003d80,0xbd6dbcc4,0x3d35bd35,0x3cc43d6d,0xbd553d0e,0xbc48bd7b,0x3d7b3c48,0xbd0e3d55,
0x3d7b3c48,0x3d553d0e,0x3d0e3d55,0x3c483d7b,0x3d800000,0x3d6d3cc4,0x3d353d35,0x3cc43d6d,0x3c48bd7b,0x3d0ebd55,0x3d55bd0e,0x3d7bbc48,0x8000bd80,0x3cc4bd6d,0x3d35bd35,0x3d6dbcc4,
0xbd7bbc48,0xbd55bd0e,0xbd0ebd55,0xbc48bd7b,0xbd800000,0xbd6dbcc4,0xbd35bd35,0xbcc4bd6d,0xbc483d7b,0xbd0e3d55,0xbd553d0e,0xbd7b3c48,0x80003d80,0xbcc43d6d,0xbd353d35,0xbd6d3cc4,
0x3d800000,0xbd800000,0x3d800000,0xbd800000,0x3d80,0xbd80,0x3d80,0xbd80,0x3d800000,0xbd800000,0x3d800000,0xbd800000,0x3d80,0xbd80,0x3d80,0xbd80,
0x3d800000,0xbd800000,0x3d800000,0xbd800000,0x3d80,0xbd80,0x3d80,0xbd80,0x3d800000,0xbd800000,0x3d800000,0xbd800000,0x3d80,0xbd80,0x3d80,0xbd80,
0x3d353d35,0xbd353d35,0xbd35bd35,0x3d35bd35,0x3d800000,0x3d80,0xbd800000,0xbd80,0x3d353d35,0xbd353d35,0xbd35bd35,0x3d35bd35,0x3d800000,0x3d80,0xbd800000,0xbd80,
0x3d353d35,0xbd353d35,0xbd35bd35,0x3d35bd35,0x3d800000,0x3d80,0xbd800000,0xbd80,0x3d353d35,0xbd353d35,0xbd35bd35,0x3d35bd35,0x3d800000,0x3d80,0xbd800000,0xbd80,
0xbd80,0x3cc43d6d,0xbd35bd35,0x3d6d3cc4,0x3d7bbc48,0xbd553d0e,0x3d0ebd55,0xbc483d7b,0x3d800000,0xbd6d3cc4,0x3d35bd35,0xbcc43d6d,0x3c483d7b,0xbd0ebd55,0x3d553d0e,0xbd7bbc48,
0x3d80,0xbcc4bd6d,0x3d353d35,0xbd6dbcc4,0xbd7b3c48,0x3d55bd0e,0xbd0e3d55,0x3c48bd7b,0xbd800000,0x3d6dbcc4,0xbd353d35,0x3cc4bd6d,0xbc48bd7b,0x3d0e3d55,0xbd55bd0e,0x3d7b3c48,
0x3d0ebd55,0x3d7b3c48,0x3c483d7b,0xbd553d0e,0xbd80,0x3d6dbcc4,0x3d353d35,0xbcc43d6d,0x3d553d0e,0xbc483d7b,0xbd7b3c48,0xbd0ebd55,0x3d800000,0x3cc43d6d,0xbd353d35,0xbd6dbcc4,
0xbd0e3d55,0xbd7bbc48,0xbc48bd7b,0x3d55bd0e,0x3d80,0xbd6d3cc4,0xbd35bd35,0x3cc4bd6d,0xbd55bd0e,0x3c48bd7b,0x3d7bbc48,0x3d0e3d55,0xbd800000,0xbcc4bd6d,0x3d35bd35,0x3d6d3cc4,
0x3d800000,0xbd353d35,0xbd80,0x3d353d35,0x3cc43d6d,0xbd6dbcc4,0x3d6dbcc4,0xbcc43d6d,0xbd800000,0x3d35bd35,0x3d80,0xbd35bd35,0xbcc4bd6d,0x3d6d3cc4,0xbd6d3cc4,0x3cc4bd6d,
0x3d800000,0xbd353d35,0xbd80,0x3d353d35,0x3cc43d6d,0xbd6dbcc4,0x3d6dbcc4,0xbcc43d6d,0xbd800000,0x3d35bd35,0x3d80,0xbd35bd35,0xbcc4bd6d,0x3d6d3cc4,0xbd6d3cc4,0x3cc4bd6d,
0x3d6d3cc4,0x3cc43d6d,0xbcc43d6d,0xbd6d3cc4,0x3d800000,0x3d353d35,0x3d80,0xbd353d35,0xbd6dbcc4,0xbcc4bd6d,0x3cc4bd6d,0x3d6dbcc4,0xbd800000,0xbd35bd35,0xbd80,0x3d35bd35,
0x3d6d3cc4,0x3cc43d6d,0xbcc43d6d,0xbd6d3cc4,0x3d800000,0x3d353d35,0x3d80,0xbd353d35,0xbd6dbcc4,0xbcc4bd6d,0x3cc4bd6d,0x3d6dbcc4,0xbd800000,0xbd35bd35,0xbd80,0x3d35bd35,
0xbd80,0x3d6d3cc4,0xbd353d35,0xbcc4bd6d,0x3d55bd0e,0x3c483d7b,0xbd7bbc48,0x3d0ebd55,0xbd800000,0x3cc4bd6d,0x3d353d35,0xbd6d3cc4,0xbd0ebd55,0x3d7bbc48,0xbc483d7b,0xbd55bd0e,
0x3d80,0xbd6dbcc4,0x3d35bd35,0x3cc43d6d,0xbd553d0e,0xbc48bd7b,0x3d7b3c48,0xbd0e3d55,0x3d800000,0xbcc43d6d,0xbd35bd35,0x3d6dbcc4,0x3d0e3d55,0xbd7b3c48,0x3c48bd7b,0x3d553d0e,
0x3c48bd7b,0x3d0ebd55,0x3d55bd0e,0x3d7bbc48,0xbd80,0x3cc4bd6d,0x3d35bd35,0x3d6dbcc4,0xbd7bbc48,0xbd55bd0e,0xbd0ebd55,0xbc48bd7b,0xbd800000,0xbd6dbcc4,0xbd35bd35,0xbcc4bd6d,
0xbc483d7b,0xbd0e3d55,0xbd553d0e,0xbd7b3c48,0x3d80,0xbcc43d6d,0xbd353d35,0xbd6d3cc4,0x3d7b3c48,0x3d553d0e,0x3d0e3d55,0x3c483d7b,0x3d800000,0x3d6d3cc4,0x3d353d35,0x3cc43d6d,
0x3d80,0x3d80,0x3d80,0x3d80,0x3d80,0x3d80,0x3d80,0x3d80,0x3d80,0x3d80,0x3d80,0x3d80,0x3d80,0x3d80,0x3d80,0x3d80,
0x3d80,0x3d80,0x3d80,0x3d80,0x3d80,0x3d80,0x3d80,0x3d80,0x3d80,0x3d80,0x3d80,0x3d80,0x3d80,0x3d80,0x3d80,0x3d80,
0xbd353d35,0xbd553d0e,0xbd6d3cc4,0xbd7b3c48,0x3d80,0xbc483d7b,0xbcc43d6d,0xbd0e3d55,0xbd35bd35,0xbd0ebd55,0xbcc4bd6d,0xbc48bd7b,0xbd800000,0xbd7bbc48,0xbd6dbcc4,0xbd55bd0e,
0x3d35bd35,0x3d55bd0e,0x3d6dbcc4,0x3d7bbc48,0xbd80,0x3c48bd7b,0x3cc4bd6d,0x3d0ebd55,0x3d353d35,0x3d0e3d55,0x3cc43d6d,0x3c483d7b,0x3d800000,0x3d7b3c48,0x3d6d3cc4,0x3d553d0e,
0xbd80,0x3cc4bd6d,0x3d35bd35,0x3d6dbcc4,0x3d800000,0x3d6d3cc4,0x3d353d35,0x3cc43d6d,0x3d80,0xbcc43d6d,0xbd353d35,0xbd6d3cc4,0xbd800000,0xbd6dbcc4,0xbd35bd35,0xbcc4bd6d,
0xbd80,0x3cc4bd6d,0x3d35bd35,0x3d6dbcc4,0x3d800000,0x3d6d3cc4,0x3d353d35,0x3cc43d6d,0x3d80,0xbcc43d6d,0xbd353d35,0xbd6d3cc4,0xbd800000,0xbd6dbcc4,0xbd35bd35,0xbcc4bd6d,
0xbd353d35,0xbd7b3c48,0xbd6dbcc4,0xbd0ebd55,0x3d800000,0x3d553d0e,0x3cc43d6d,0xbc483d7b,0xbd35bd35,0xbc48bd7b,0x3cc4bd6d,0x3d55bd0e,0x3d80,0xbd0e3d55,0xbd6d3cc4,0xbd7bbc48,
0x3d35bd35,0x3d7bbc48,0x3d6d3cc4,0x3d0e3d55,0xbd800000,0xbd55bd0e,0xbcc4bd6d,0x3c48bd7b,0x3d353d35,0x3c483d7b,0xbcc43d6d,0xbd553d0e,0xbd80,0x3d0ebd55,0x3d6dbcc4,0x3d7b3c48,
0x3d80,0xbd353d35,0xbd800000,0xbd35bd35,0xbd80,0x3d35bd35,0x3d800000,0x3d353d35,0x3d80,0xbd353d35,0xbd800000,0xbd35bd35,0xbd80,0x3d35bd35,0x3d800000,0x3d353d35,
0x3d80,0xbd353d35,0xbd800000,0xbd35bd35,0xbd80,0x3d35bd35,0x3d800000,0x3d353d35,0x3d80,0xbd353d35,0xbd800000,0xbd35bd35,0xbd80,0x3d35bd35,0x3d800000,0x3d353d35,
0xbd353d35,0xbd7bbc48,0xbcc4bd6d,0x3d0ebd55,0xbd80,0x3d55bd0e,0x3d6d3cc4,0x3c483d7b,0xbd35bd35,0x3c48bd7b,0x3d6dbcc4,0x3d553d0e,0x3d800000,0x3d0e3d55,0xbcc43d6d,0xbd7b3c48,
0x3d35bd35,0x3d7b3c48,0x3cc43d6d,0xbd0e3d55,0x3d80,0xbd553d0e,0xbd6dbcc4,0xbc48bd7b,0x3d353d35,0xbc483d7b,0xbd6d3cc4,0xbd55bd0e,0xbd800000,0xbd0ebd55,0x3cc4bd6d,0x3d7bbc48,
0xbd80,0x3d6dbcc4,0x3d353d35,0xbcc43d6d,0xbd800000,0xbcc4bd6d,0x3d35bd35,0x3d6d3cc4,0x3d80,0xbd6d3cc4,0xbd35bd35,0x3cc4bd6d,0x3d800000,0x3cc43d6d,0xbd353d35,0xbd6dbcc4,
0xbd80,0x3d6dbcc4,0x3d353d35,0xbcc43d6d,0xbd800000,0xbcc4bd6d,0x3d35bd35,0x3d6d3cc4,0x3d80,0xbd6d3cc4,0xbd35bd35,0x3cc4bd6d,0x3d800000,0x3cc43d6d,0xbd353d35,0xbd6dbcc4,
0xbd353d35,0xbd55bd0e,0x3cc4bd6d,0x3d7b3c48,0xbd800000,0xbc48bd7b,0x3d6dbcc4,0x3d0e3d55,0xbd35bd35,0x3d0ebd55,0x3d6d3cc4,0xbc483d7b,0xbd80,0x3d7bbc48,0x3cc43d6d,0xbd553d0e,
0x3d35bd35,0x3d553d0e,0xbcc43d6d,0xbd7bbc48,0x3d800000,0x3c483d7b,0xbd6d3cc4,0xbd0ebd55,0x3d353d35,0xbd0e3d55,0xbd6dbcc4,0x3c48bd7b,0x3d80,0xbd7b3c48,0xbcc4bd6d,0x3d55bd0e,
0xbd800000,0xbd800000,0xbd800000,0xbd800000,0xbd800000,0xbd800000,0xbd800000,0xbd800000,0xbd800000,0xbd800000,0xbd800000,0xbd800000,0xbd800000,0xbd800000,0xbd800000,0xbd800000,
0xbd800000,0xbd800000,0xbd800000,0xbd800000,0xbd800000,0xbd800000,0xbd800000,0xbd800000,0xbd800000,0xbd800000,0xbd800000,0xbd800000,0xbd800000,0xbd800000,0xbd800000,0xbd800000,
0xbd35bd35,0xbd0ebd55,0xbcc4bd6d,0xbc48bd7b,0xbd800000,0xbd7bbc48,0xbd6dbcc4,0xbd55bd0e,0x3d35bd35,0x3d55bd0e,0x3d6dbcc4,0x3d7bbc48,0x8000bd80,0x3c48bd7b,0x3cc4bd6d,0x3d0ebd55,
0x3d353d35,0x3d0e3d55,0x3cc43d6d,0x3c483d7b,0x3d800000,0x3d7b3c48,0x3d6d3cc4,0x3d553d0e,0xbd353d35,0xbd553d0e,0xbd6d3cc4,0xbd7b3c48,0x80003d80,0xbc483d7b,0xbcc43d6d,0xbd0e3d55,
0x3d800000,0x3d6d3cc4,0x3d353d35,0x3cc43d6d,0x80003d80,0xbcc43d6d,0xbd353d35,0xbd6d3cc4,0xbd800000,0xbd6dbcc4,0xbd35bd35,0xbcc4bd6d,0x8000bd80,0x3cc4bd6d,0x3d35bd35,0x3d6dbcc4,
0x3d800000,0x3d6d3cc4,0x3d353d35,0x3cc43d6d,0x80003d80,0xbcc43d6d,0xbd353d35,0xbd6d3cc4,0xbd800000,0xbd6dbcc4,0xbd35bd35,0xbcc4bd6d,0x8000bd80,0x3cc4bd6d,0x3d35bd35,0x3d6dbcc4,
0xbd35bd35,0xbc48bd7b,0x3cc4bd6d,0x3d55bd0e,0x80003d80,0xbd0e3d55,0xbd6d3cc4,0xbd7bbc48,0x3d35bd35,0x3d7bbc48,0x3d6d3cc4,0x3d0e3d55,0xbd800000,0xbd55bd0e,0xbcc4bd6d,0x3c48bd7b,
0x3d353d35,0x3c483d7b,0xbcc43d6d,0xbd553d0e,0x8000bd80,0x3d0ebd55,0x3d6dbcc4,0x3d7b3c48,0xbd353d35,0xbd7b3c48,0xbd6dbcc4,0xbd0ebd55,0x3d800000,0x3d553d0e,0x3cc43d6d,0xbc483d7b,
0xbd800000,0xbd35bd35,0x8000bd80,0x3d35bd35,0x3d800000,0x3d353d35,0x80003d80,0xbd353d35,0xbd800000,0xbd35bd35,0x8000bd80,0x3d35bd35,0x3d800000,0x3d353d35,0x80003d80,0xbd353d35,
0xbd800000,0xbd35bd35,0x8000bd80,0x3d35bd35,0x3d800000,0x3d353d35,0x80003d80,0xbd353d35,0xbd800000,0xbd35bd35,0x8000bd80,0x3d35bd35,0x3d800000,0x3d353d35,0x80003d80,0xbd353d35,
0xbd35bd35,0x3c48bd7b,0x3d6dbcc4,0x3d553d0e,0x3d800000,0x3d0e3d55,0xbcc43d6d,0xbd7b3c48,0x3d35bd35,0x3d7b3c48,0x3cc43d6d,0xbd0e3d55,0x80003d80,0xbd553d0e,0xbd6dbcc4,0xbc48bd7b,
0x3d353d35,0xbc483d7b,0xbd6d3cc4,0xbd55bd0e,0xbd800000,0xbd0ebd55,0x3cc4bd6d,0x3d7bbc48,0xbd353d35,0xbd7bbc48,0xbcc4bd6d,0x3d0ebd55,0x8000bd80,0x3d55bd0e,0x3d6d3cc4,0x3c483d7b,
0x3d800000,0x3cc43d6d,0xbd353d35,0xbd6dbcc4,0x8000bd80,0x3d6dbcc4,0x3d353d35,0xbcc43d6d,0xbd800000,0xbcc4bd6d,0x3d35bd35,0x3d6d3cc4,0x80003d80,0xbd6d3cc4,0xbd35bd35,0x3cc4bd6d,
0x3d800000,0x3cc43d6d,0xbd353d35,0xbd6dbcc4,0x8000bd80,0x3d6dbcc4,0x3d353d35,0xbcc43d6d,0xbd800000,0xbcc4bd6d,0x3d35bd35,0x3d6d3cc4,0x80003d80,0xbd6d3cc4,0xbd35bd35,0x3cc4bd6d,
0xbd35bd35,0x3d0ebd55,0x3d6d3cc4,0xbc483d7b,0x8000bd80,0x3d7bbc48,0x3cc43d6d,0xbd553d0e,0x3d35bd35,0x3d553d0e,0xbcc43d6d,0xbd7bbc48,0x3d800000,0x3c483d7b,0xbd6d3cc4,0xbd0ebd55,
0x3d353d35,0xbd0e3d55,0xbd6dbcc4,0x3c48bd7b,0x80003d80,0xbd7b3c48,0xbcc4bd6d,0x3d55bd0e,0xbd353d35,0xbd55bd0e,0x3cc4bd6d,0x3d7b3c48,0xbd800000,0xbc48bd7b,0x3d6dbcc4,0x3d0e3d55,
0x3d80,0xbd800000,0xbd80,0x3d800000,0x3d80,0xbd800000,0xbd80,0x3d800000,0x3d80,0xbd800000,0xbd80,0x3d800000,0x3d80,0xbd800000,0xbd80,0x3d800000,
0x3d80,0xbd800000,0xbd80,0x3d800000,0x3d80,0xbd800000,0xbd80,0x3d800000,0x3d80,0xbd800000,0xbd80,0x3d800000,0x3d80,0xbd800000,0xbd80,0x3d800000,
0xbd353d35,0xbd0ebd55,0x3d6dbcc4,0x3c483d7b,0x3d80,0xbd7bbc48,0x3cc4bd6d,0x3d553d0e,0xbd35bd35,0x3d55bd0e,0x3cc43d6d,0xbd7b3c48,0xbd800000,0x3c48bd7b,0x3d6d3cc4,0xbd0e3d55,
0x3d35bd35,0x3d0e3d55,0xbd6d3cc4,0xbc48bd7b,0xbd80,0x3d7b3c48,0xbcc43d6d,0xbd55bd0e,0x3d353d35,0xbd553d0e,0xbcc4bd6d,0x3d7bbc48,0x3d800000,0xbc483d7b,0xbd6dbcc4,0x3d0ebd55,
0xbd80,0x3d6d3cc4,0xbd353d35,0xbcc4bd6d,0x3d800000,0xbcc43d6d,0xbd35bd35,0x3d6dbcc4,0x3d80,0xbd6dbcc4,0x3d35bd35,0x3cc43d6d,0xbd800000,0x3cc4bd6d,0x3d353d35,0xbd6d3cc4,
0xbd80,0x3d6d3cc4,0xbd353d35,0xbcc4bd6d,0x3d800000,0xbcc43d6d,0xbd35bd35,0x3d6dbcc4,0x3d80,0xbd6dbcc4,0x3d35bd35,0x3cc43d6d,0xbd800000,0x3cc4bd6d,0x3d353d35,0xbd6d3cc4,
0xbd353d35,0xbc48bd7b,0x3d6d3cc4,0xbd553d0e,0x3d800000,0xbd0e3d55,0xbcc4bd6d,0x3d7b3c48,0xbd35bd35,0x3d7bbc48,0xbcc43d6d,0xbd0ebd55,0x3d80,0xbd55bd0e,0x3d6dbcc4,0xbc483d7b,
0x3d35bd35,0x3c483d7b,0xbd6dbcc4,0x3d55bd0e,0xbd800000,0x3d0ebd55,0x3cc43d6d,0xbd7bbc48,0x3d353d35,0xbd7b3c48,0x3cc4bd6d,0x3d0e3d55,0xbd80,0x3d553d0e,0xbd6d3cc4,0x3c48bd7b,
0x3d80,0xbd35bd35,0x3d800000,0xbd353d35,0xbd80,0x3d353d35,0xbd800000,0x3d35bd35,0x3d80,0xbd35bd35,0x3d800000,0xbd353d35,0xbd80,0x3d353d35,0xbd800000,0x3d35bd35,
0x3d80,0xbd35bd35,0x3d800000,0xbd353d35,0xbd80,0x3d353d35,0xbd800000,0x3d35bd35,0x3d80,0xbd35bd35,0x3d800000,0xbd353d35,0xbd80,0x3d353d35,0xbd800000,0x3d35bd35,
0xbd353d35,0x3c48bd7b,0x3cc43d6d,0xbd55bd0e,0xbd80,0x3d0e3d55,0xbd6dbcc4,0x3d7bbc48,0xbd35bd35,0x3d7b3c48,0xbd6d3cc4,0x3d0ebd55,0x3d800000,0xbd553d0e,0x3cc4bd6d,0x3c483d7b,
0x3d35bd35,0xbc483d7b,0xbcc4bd6d,0x3d553d0e,0x3d80,0xbd0ebd55,0x3d6d3cc4,0xbd7b3c48,0x3d353d35,0xbd7bbc48,0x3d6dbcc4,0xbd0e3d55,0xbd800000,0x3d55bd0e,0xbcc43d6d,0xbc48bd7b,
0xbd80,0x3cc43d6d,0xbd35bd35,0x3d6d3cc4,0xbd800000,0x3d6dbcc4,0xbd353d35,0x3cc4bd6d,0x3d80,0xbcc4bd6d,0x3d353d35,0xbd6dbcc4,0x3d800000,0xbd6d3cc4,0x3d35bd35,0xbcc43d6d,
0xbd80,0x3cc43d6d,0xbd35bd35,0x3d6d3cc4,0xbd800000,0x3d6dbcc4,0xbd353d35,0x3cc4bd6d,0x3d80,0xbcc4bd6d,0x3d353d35,0xbd6dbcc4,0x3d800000,0xbd6d3cc4,0x3d35bd35,0xbcc43d6d,
0xbd353d35,0x3d0ebd55,0xbcc43d6d,0x3c48bd7b,0xbd800000,0x3d7bbc48,0xbd6d3cc4,0x3d55bd0e,0xbd35bd35,0x3d553d0e,0xbd6dbcc4,0x3d7b3c48,0xbd80,0x3c483d7b,0xbcc4bd6d,0x3d0e3d55,
0x3d35bd35,0xbd0e3d55,0x3cc4bd6d,0xbc483d7b,0x3d800000,0xbd7b3c48,0x3d6dbcc4,0xbd553d0e,0x3d353d35,0xbd55bd0e,0x3d6d3cc4,0xbd7bbc48,0x3d80,0xbc48bd7b,0x3cc43d6d,0xbd0ebd55,
0xbd800000,0x8000bd80,0x3d800000,0x80003d80,0xbd800000,0x8000bd80,0x3d800000,0x80003d80,0xbd800000,0x8000bd80,0x3d800000,0x80003d80,0xbd800000,0x8000bd80,0x3d800000,0x80003d80,
0xbd800000,0x8000bd80,0x3d800000,0x80003d80,0xbd800000,0x8000bd80,0x3d800000,0x80003d80,0xbd800000,0x8000bd80,0x3d800000,0x80003d80,0xbd800000,0x8000bd80,0x3d800000,0x80003d80,
0xbd35bd35,0x3d55bd0e,0x3cc43d6d,0xbd7b3c48,0xbd800000,0x3c48bd7b,0x3d6d3cc4,0xbd0e3d55,0x3d35bd35,0x3d0e3d55,0xbd6d3cc4,0xbc48bd7b,0x8000bd80,0x3d7b3c48,0xbcc43d6d,0xbd55bd0e,
0x3d353d35,0xbd553d0e,0xbcc4bd6d,0x3d7bbc48,0x3d800000,0xbc483d7b,0xbd6dbcc4,0x3d0ebd55,0xbd353d35,0xbd0ebd55,0x3d6dbcc4,0x3c483d7b,0x80003d80,0xbd7bbc48,0x3cc4bd6d,0x3d553d0e,
0x3d800000,0xbcc43d6d,0xbd35bd35,0x3d6dbcc4,0x80003d80,0xbd6dbcc4,0x3d35bd35,0x3cc43d6d,0xbd800000,0x3cc4bd6d,0x3d353d35,0xbd6d3cc4,0x8000bd80,0x3d6d3cc4,0xbd353d35,0xbcc4bd6d,
0x3d800000,0xbcc43d6d,0xbd35bd35,0x3d6dbcc4,0x80003d80,0xbd6dbcc4,0x3d35bd35,0x3cc43d6d,0xbd800000,0x3cc4bd6d,0x3d353d35,0xbd6d3cc4,0x8000bd80,0x3d6d3cc4,0xbd353d35,0xbcc4bd6d,
0xbd35bd35,0x3d7bbc48,0xbcc43d6d,0xbd0ebd55,0x80003d80,0xbd55bd0e,0x3d6dbcc4,0xbc483d7b,0x3d35bd35,0x3c483d7b,0xbd6dbcc4,0x3d55bd0e,0xbd800000,0x3d0ebd55,0x3cc43d6d,0xbd7bbc48,
0x3d353d35,0xbd7b3c48,0x3cc4bd6d,0x3d0e3d55,0x8000bd80,0x3d553d0e,0xbd6d3cc4,0x3c48bd7b,0xbd353d35,0xbc48bd7b,0x3d6d3cc4,0xbd553d0e,0x3d800000,0xbd0e3d55,0xbcc4bd6d,0x3d7b3c48,
0xbd800000,0x3d35bd35,0x80003d80,0xbd35bd35,0x3d800000,0xbd353d35,0x8000bd80,0x3d353d35,0xbd800000,0x3d35bd35,0x80003d80,0xbd35bd35,0x3d800000,0xbd353d35,0x8000bd80,0x3d353d35,
0xbd800000,0x3d35bd35,0x80003d80,0xbd35bd35,0x3d800000,0xbd353d35,0x8000bd80,0x3d353d35,0xbd800000,0x3d35bd35,0x80003d80,0xbd35bd35,0x3d800000,0xbd353d35,0x8000bd80,0x3d353d35,
0xbd35bd35,0x3d7b3c48,0xbd6d3cc4,0x3d0ebd55,0x3d800000,0xbd553d0e,0x3cc4bd6d,0x3c483d7b,0x3d35bd35,0xbc483d7b,0xbcc4bd6d,0x3d553d0e,0x80003d80,0xbd0ebd55,0x3d6d3cc4,0xbd7b3c48,
0x3d353d35,0xbd7bbc48,0x3d6dbcc4,0xbd0e3d55,0xbd800000,0x3d55bd0e,0xbcc43d6d,0xbc48bd7b,0xbd353d35,0x3c48bd7b,0x3cc43d6d,0xbd55bd0e,0x8000bd80,0x3d0e3d55,0xbd6dbcc4,0x3d7bbc48,
0x3d800000,0xbd6d3cc4,0x3d35bd35,0xbcc43d6d,0x8000bd80,0x3cc43d6d,0xbd35bd35,0x3d6d3cc4,0xbd800000,0x3d6dbcc4,0xbd353d35,0x3cc4bd6d,0x80003d80,0xbcc4bd6d,0x3d353d35,0xbd6dbcc4,
0x3d800000,0xbd6d3cc4,0x3d35bd35,0xbcc43d6d,0x8000bd80,0x3cc43d6d,0xbd35bd35,0x3d6d3cc4,0xbd800000,0x3d6dbcc4,0xbd353d35,0x3cc4bd6d,0x80003d80,0xbcc4bd6d,0x3d353d35,0xbd6dbcc4,
0xbd35bd35,0x3d553d0e,0xbd6dbcc4,0x3d7b3c48,0x8000bd80,0x3c483d7b,0xbcc4bd6d,0x3d0e3d55,0x3d35bd35,0xbd0e3d55,0x3cc4bd6d,0xbc483d7b,0x3d800000,0xbd7b3c48,0x3d6dbcc4,0xbd553d0e,
0x3d353d35,0xbd55bd0e,0x3d6d3cc4,0xbd7bbc48,0x80003d80,0xbc48bd7b,0x3cc43d6d,0xbd0ebd55,0xbd353d35,0x3d0ebd55,0xbcc43d6d,0x3c48bd7b,0xbd800000,0x3d7bbc48,0xbd6d3cc4,0x3d55bd0e,
0x3d80,0xbd80,0x3d80,0xbd80,0x3d80,0xbd80,0x3d80,0xbd80,0x3d80,0xbd80,0x3d80,0xbd80,0x3d80,0xbd80,0x3d80,0xbd80,
0x3d80,0xbd80,0x3d80,0xbd80,0x3d80,0xbd80,0x3d80,0xbd80,0x3d80,0xbd80,0x3d80,0xbd80,0x3d80,0xbd80,0x3d80,0xbd80,
0xbd353d35,0x3d55bd0e,0xbd6d3cc4,0x3d7bbc48,0x3d80,0x3c48bd7b,0xbcc43d6d,0x3d0ebd55,0xbd35bd35,0x3d0e3d55,0xbcc4bd6d,0x3c483d7b,0xbd800000,0x3d7b3c48,0xbd6dbcc4,0x3d553d0e,
0x3d35bd35,0xbd553d0e,0x3d6dbcc4,0xbd7b3c48,0xbd80,0xbc483d7b,0x3cc4bd6d,0xbd0e3d55,0x3d353d35,0xbd0ebd55,0x3cc43d6d,0xbc48bd7b,0x3d800000,0xbd7bbc48,0x3d6d3cc4,0xbd55bd0e,
0xbd80,0xbcc43d6d,0x3d35bd35,0xbd6d3cc4,0x3d800000,0xbd6dbcc4,0x3d353d35,0xbcc4bd6d,0x3d80,0x3cc4bd6d,0xbd353d35,0x3d6dbcc4,0xbd800000,0x3d6d3cc4,0xbd35bd35,0x3cc43d6d,
0xbd80,0xbcc43d6d,0x3d35bd35,0xbd6d3cc4,0x3d800000,0xbd6dbcc4,0x3d353d35,0xbcc4bd6d,0x3d80,0x3cc4bd6d,0xbd353d35,0x3d6dbcc4,0xbd800000,0x3d6d3cc4,0xbd35bd35,0x3cc43d6d,
0xbd353d35,0x3d7bbc48,0xbd6dbcc4,0x3d0e3d55,0x3d800000,0xbd55bd0e,0x3cc43d6d,0x3c48bd7b,0xbd35bd35,0x3c483d7b,0x3cc4bd6d,0xbd553d0e,0x3d80,0x3d0ebd55,0xbd6d3cc4,0x3d7b3c48,
0x3d35bd35,0xbd7b3c48,0x3d6d3cc4,0xbd0ebd55,0xbd800000,0x3d553d0e,0xbcc4bd6d,0xbc483d7b,0x3d353d35,0xbc48bd7b,0xbcc43d6d,0x3d55bd0e,0xbd80,0xbd0e3d55,0x3d6dbcc4,0xbd7bbc48,
0x3d80,0x3d35bd35,0xbd800000,0x3d353d35,0xbd80,0xbd353d35,0x3d800000,0xbd35bd35,0x3d80,0x3d35bd35,0xbd800000,0x3d353d35,0xbd80,0xbd353d35,0x3d800000,0xbd35bd35,
0x3d80,0x3d35bd35,0xbd800000,0x3d353d35,0xbd80,0xbd353d35,0x3d800000,0xbd35bd35,0x3d80,0x3d35bd35,0xbd800000,0x3d353d35,0xbd80,0xbd353d35,0x3d800000,0xbd35bd35,
0xbd353d35,0x3d7b3c48,0xbcc4bd6d,0xbd0e3d55,0xbd80,0xbd553d0e,0x3d6d3cc4,0xbc48bd7b,0xbd35bd35,0xbc483d7b,0x3d6dbcc4,0xbd55bd0e,0x3d800000,0xbd0ebd55,0xbcc43d6d,0x3d7bbc48,
0x3d35bd35,0xbd7bbc48,0x3cc43d6d,0x3d0ebd55,0x3d80,0x3d55bd0e,0xbd6dbcc4,0x3c483d7b,0x3d353d35,0x3c48bd7b,0xbd6d3cc4,0x3d553d0e,0xbd800000,0x3d0e3d55,0x3cc4bd6d,0xbd7b3c48,
0xbd80,0xbd6d3cc4,0x3d353d35,0x3cc4bd6d,0xbd800000,0x3cc43d6d,0x3d35bd35,0xbd6dbcc4,0x3d80,0x3d6dbcc4,0xbd35bd35,0xbcc43d6d,0x3d800000,0xbcc4bd6d,0xbd353d35,0x3d6d3cc4,
0xbd80,0xbd6d3cc4,0x3d353d35,0x3cc4bd6d,0xbd800000,0x3cc43d6d,0x3d35bd35,0xbd6dbcc4,0x3d80,0x3d6dbcc4,0xbd35bd35,0xbcc43d6d,0x3d800000,0xbcc4bd6d,0xbd353d35,0x3d6d3cc4,
0xbd353d35,0x3d553d0e,0x3cc4bd6d,0xbd7bbc48,0xbd800000,0x3c483d7b,0x3d6dbcc4,0xbd0ebd55,0xbd35bd35,0xbd0e3d55,0x3d6d3cc4,0x3c48bd7b,0xbd80,0xbd7b3c48,0x3cc43d6d,0x3d55bd0e,
0x3d35bd35,0xbd55bd0e,0xbcc43d6d,0x3d7b3c48,0x3d800000,0xbc48bd7b,0xbd6d3cc4,0x3d0e3d55,0x3d353d35,0x3d0ebd55,0xbd6dbcc4,0xbc483d7b,0x3d80,0x3d7bbc48,0xbcc4bd6d,0xbd553d0e,
0xbd800000,0x3d800000,0xbd800000,0x3d800000,0xbd800000,0x3d800000,0xbd800000,0x3d800000,0xbd800000,0x3d800000,0xbd800000,0x3d800000,0xbd800000,0x3d800000,0xbd800000,0x3d800000,
0xbd800000,0x3d800000,0xbd800000,0x3d800000,0xbd800000,0x3d800000,0xbd800000,0x3d800000,0xbd800000,0x3d800000,0xbd800000,0x3d800000,0xbd800000,0x3d800000,0xbd800000,0x3d800000,
0xbd35bd35,0x3d0e3d55,0xbcc4bd6d,0x3c483d7b,0xbd800000,0x3d7b3c48,0xbd6dbcc4,0x3d553d0e,0x3d35bd35,0xbd553d0e,0x3d6dbcc4,0xbd7b3c48,0x8000bd80,0xbc483d7b,0x3cc4bd6d,0xbd0e3d55,
0x3d353d35,0xbd0ebd55,0x3cc43d6d,0xbc48bd7b,0x3d800000,0xbd7bbc48,0x3d6d3cc4,0xbd55bd0e,0xbd353d35,0x3d55bd0e,0xbd6d3cc4,0x3d7bbc48,0x80003d80,0x3c48bd7b,0xbcc43d6d,0x3d0ebd55,
0x3d800000,0xbd6dbcc4,0x3d353d35,0xbcc4bd6d,0x80003d80,0x3cc4bd6d,0xbd353d35,0x3d6dbcc4,0xbd800000,0x3d6d3cc4,0xbd35bd35,0x3cc43d6d,0x8000bd80,0xbcc43d6d,0x3d35bd35,0xbd6d3cc4,
0x3d800000,0xbd6dbcc4,0x3d353d35,0xbcc4bd6d,0x80003d80,0x3cc4bd6d,0xbd353d35,0x3d6dbcc4,0xbd800000,0x3d6d3cc4,0xbd35bd35,0x3cc43d6d,0x8000bd80,0xbcc43d6d,0x3d35bd35,0xbd6d3cc4,
0xbd35bd35,0x3c483d7b,0x3cc4bd6d,0xbd553d0e,0x80003d80,0x3d0ebd55,0xbd6d3cc4,0x3d7b3c48,0x3d35bd35,0xbd7b3c48,0x3d6d3cc4,0xbd0ebd55,0xbd800000,0x3d553d0e,0xbcc4bd6d,0xbc483d7b,
0x3d353d35,0xbc48bd7b,0xbcc43d6d,0x3d55bd0e,0x8000bd80,0xbd0e3d55,0x3d6dbcc4,0xbd7bbc48,0xbd353d35,0x3d7bbc48,0xbd6dbcc4,0x3d0e3d55,0x3d800000,0xbd55bd0e,0x3cc43d6d,0x3c48bd7b,
0xbd800000,0x3d353d35,0x8000bd80,0xbd353d35,0x3d800000,0xbd35bd35,0x80003d80,0x3d35bd35,0xbd800000,0x3d353d35,0x8000bd80,0xbd353d35,0x3d800000,0xbd35bd35,0x80003d80,0x3d35bd35,
0xbd800000,0x3d353d35,0x8000bd80,0xbd353d35,0x3d800000,0xbd35bd35,0x80003d80,0x3d35bd35,0xbd800000,0x3d353d35,0x8000bd80,0xbd353d35,0x3d800000,0xbd35bd35,0x80003d80,0x3d35bd35,
0xbd35bd35,0xbc483d7b,0x3d6dbcc4,0xbd55bd0e,0x3d800000,0xbd0ebd55,0xbcc43d6d,0x3d7bbc48,0x3d35bd35,0xbd7bbc48,0x3cc43d6d,0x3d0ebd55,0x80003d80,0x3d55bd0e,0xbd6dbcc4,0x3c483d7b,
0x3d353d35,0x3c48bd7b,0xbd6d3cc4,0x3d553d0e,0xbd800000,0x3d0e3d55,0x3cc4bd6d,0xbd7b3c48,0xbd353d35,0x3d7b3c48,0xbcc4bd6d,0xbd0e3d55,0x8000bd80,0xbd553d0e,0x3d6d3cc4,0xbc48bd7b,
0x3d800000,0xbcc4bd6d,0xbd353d35,0x3d6d3cc4,0x8000bd80,0xbd6d3cc4,0x3d353d35,0x3cc4bd6d,0xbd800000,0x3cc43d6d,0x3d35bd35,0xbd6dbcc4,0x80003d80,0x3d6dbcc4,0xbd35bd35,0xbcc43d6d,
0x3d800000,0xbcc4bd6d,0xbd353d35,0x3d6d3cc4,0x8000bd80,0xbd6d3cc4,0x3d353d35,0x3cc4bd6d,0xbd800000,0x3cc43d6d,0x3d35bd35,0xbd6dbcc4,0x80003d80,0x3d6dbcc4,0xbd35bd35,0xbcc43d6d,
0xbd35bd35,0xbd0e3d55,0x3d6d3cc4,0x3c48bd7b,0x8000bd80,0xbd7b3c48,0x3cc43d6d,0x3d55bd0e,0x3d35bd35,0xbd55bd0e,0xbcc43d6d,0x3d7b3c48,0x3d800000,0xbc48bd7b,0xbd6d3cc4,0x3d0e3d55,
0x3d353d35,0x3d0ebd55,0xbd6dbcc4,0xbc483d7b,0x80003d80,0x3d7bbc48,0xbcc4bd6d,0xbd553d0e,0xbd353d35,0x3d553d0e,0x3cc4bd6d,0xbd7bbc48,0xbd800000,0x3c483d7b,0x3d6dbcc4,0xbd0ebd55,
0x3d80,0x3d800000,0xbd80,0xbd800000,0x3d80,0x3d800000,0xbd80,0xbd800000,0x3d80,0x3d800000,0xbd80,0xbd800000,0x3d80,0x3d800000,0xbd80,0xbd800000,
0x3d80,0x3d800000,0xbd80,0xbd800000,0x3d80,0x3d800000,0xbd80,0xbd800000,0x3d80,0x3d800000,0xbd80,0xbd800000,0x3d80,0x3d800000,0xbd80,0xbd800000,
0xbd353d35,0x3d0e3d55,0x3d6dbcc4,0xbc48bd7b,0x3d80,0x3d7b3c48,0x3cc4bd6d,0xbd55bd0e,0xbd35bd35,0xbd553d0e,0x3cc43d6d,0x3d7bbc48,0xbd800000,0xbc483d7b,0x3d6d3cc4,0x3d0ebd55,
0x3d35bd35,0xbd0ebd55,0xbd6d3cc4,0x3c483d7b,0xbd80,0xbd7bbc48,0xbcc43d6d,0x3d553d0e,0x3d353d35,0x3d55bd0e,0xbcc4bd6d,0xbd7b3c48,0x3d800000,0x3c48bd7b,0xbd6dbcc4,0xbd0e3d55,
0xbd80,0xbd6dbcc4,0xbd353d35,0x3cc43d6d,0x3d800000,0x3cc4bd6d,0xbd35bd35,0xbd6d3cc4,0x3d80,0x3d6d3cc4,0x3d35bd35,0xbcc4bd6d,0xbd800000,0xbcc43d6d,0x3d353d35,0x3d6dbcc4,
0xbd80,0xbd6dbcc4,0xbd353d35,0x3cc43d6d,0x3d800000,0x3cc4bd6d,0xbd35bd35,0xbd6d3cc4,0x3d80,0x3d6d3cc4,0x3d35bd35,0xbcc4bd6d,0xbd800000,0xbcc43d6d,0x3d353d35,0x3d6dbcc4,
0xbd353d35,0x3c483d7b,0x3d6d3cc4,0x3d55bd0e,0x3d800000,0x3d0ebd55,0xbcc4bd6d,0xbd7bbc48,0xbd35bd35,0xbd7b3c48,0xbcc43d6d,0x3d0e3d55,0x3d80,0x3d553d0e,0x3d6dbcc4,0x3c48bd7b,
0x3d35bd35,0xbc48bd7b,0xbd6dbcc4,0xbd553d0e,0xbd800000,0xbd0e3d55,0x3cc43d6d,0x3d7b3c48,0x3d353d35,0x3d7bbc48,0x3cc4bd6d,0xbd0ebd55,0xbd80,0xbd55bd0e,0xbd6d3cc4,0xbc483d7b,
0x3d80,0x3d353d35,0x3d800000,0x3d35bd35,0xbd80,0xbd35bd35,0xbd800000,0xbd353d35,0x3d80,0x3d353d35,0x3d800000,0x3d35bd35,0xbd80,0xbd35bd35,0xbd800000,0xbd353d35,
0x3d80,0x3d353d35,0x3d800000,0x3d35bd35,0xbd80,0xbd35bd35,0xbd800000,0xbd353d35,0x3d80,0x3d353d35,0x3d800000,0x3d35bd35,0xbd80,0xbd35bd35,0xbd800000,0xbd353d35,
0xbd353d35,0xbc483d7b,0x3cc43d6d,0x3d553d0e,0xbd80,0xbd0ebd55,0xbd6dbcc4,0xbd7b3c48,0xbd35bd35,0xbd7bbc48,0xbd6d3cc4,0xbd0e3d55,0x3d800000,0x3d55bd0e,0x3cc4bd6d,0xbc48bd7b,
0x3d35bd35,0x3c48bd7b,0xbcc4bd6d,0xbd55bd0e,0x3d80,0x3d0e3d55,0x3d6d3cc4,0x3d7bbc48,0x3d353d35,0x3d7b3c48,0x3d6dbcc4,0x3d0ebd55,0xbd800000,0xbd553d0e,0xbcc43d6d,0x3c483d7b,
0xbd80,0xbcc4bd6d,0xbd35bd35,0xbd6dbcc4,0xbd800000,0xbd6d3cc4,0xbd353d35,0xbcc43d6d,0x3d80,0x3cc43d6d,0x3d353d35,0x3d6d3cc4,0x3d800000,0x3d6dbcc4,0x3d35bd35,0x3cc4bd6d,
0xbd80,0xbcc4bd6d,0xbd35bd35,0xbd6dbcc4,0xbd800000,0xbd6d3cc4,0xbd353d35,0xbcc43d6d,0x3d80,0x3cc43d6d,0x3d353d35,0x3d6d3cc4,0x3d800000,0x3d6dbcc4,0x3d35bd35,0x3cc4bd6d,
0xbd353d35,0xbd0e3d55,0xbcc43d6d,0xbc483d7b,0xbd800000,0xbd7b3c48,0xbd6d3cc4,0xbd553d0e,0xbd35bd35,0xbd55bd0e,0xbd6dbcc4,0xbd7bbc48,0xbd80,0xbc48bd7b,0xbcc4bd6d,0xbd0ebd55,
0x3d35bd35,0x3d0ebd55,0x3cc4bd6d,0x3c48bd7b,0x3d800000,0x3d7bbc48,0x3d6dbcc4,0x3d55bd0e,0x3d353d35,0x3d553d0e,0x3d6d3cc4,0x3d7b3c48,0x3d80,0x3c483d7b,0x3cc43d6d,0x3d0e3d55,
0xbd800000,0x80003d80,0x3d800000,0x8000bd80,0xbd800000,0x80003d80,0x3d800000,0x8000bd80,0xbd800000,0x80003d80,0x3d800000,0x8000bd80,0xbd800000,0x80003d80,0x3d800000,0x8000bd80,
0xbd800000,0x80003d80,0x3d800000,0x8000bd80,0xbd800000,0x80003d80,0x3d800000,0x8000bd80,0xbd800000,0x80003d80,0x3d800000,0x8000bd80,0xbd800000,0x80003d80,0x3d800000,0x8000bd80,
0xbd35bd35,0xbd553d0e,0x3cc43d6d,0x3d7bbc48,0xbd800000,0xbc483d7b,0x3d6d3cc4,0x3d0ebd55,0x3d35bd35,0xbd0ebd55,0xbd6d3cc4,0x3c483d7b,0x8000bd80,0xbd7bbc48,0xbcc43d6d,0x3d553d0e,
0x3d353d35,0x3d55bd0e,0xbcc4bd6d,0xbd7b3c48,0x3d800000,0x3c48bd7b,0xbd6dbcc4,0xbd0e3d55,0xbd353d35,0x3d0e3d55,0x3d6dbcc4,0xbc48bd7b,0x80003d80,0x3d7b3c48,0x3cc4bd6d,0xbd55bd0e,
0x3d800000,0x3cc4bd6d,0xbd35bd35,0xbd6d3cc4,0x80003d80,0x3d6d3cc4,0x3d35bd35,0xbcc4bd6d,0xbd800000,0xbcc43d6d,0x3d353d35,0x3d6dbcc4,0x8000bd80,0xbd6dbcc4,0xbd353d35,0x3cc43d6d,
0x3d800000,0x3cc4bd6d,0xbd35bd35,0xbd6d3cc4,0x80003d80,0x3d6d3cc4,0x3d35bd35,0xbcc4bd6d,0xbd800000,0xbcc43d6d,0x3d353d35,0x3d6dbcc4,0x8000bd80,0xbd6dbcc4,0xbd353d35,0x3cc43d6d,
0xbd35bd35,0xbd7b3c48,0xbcc43d6d,0x3d0e3d55,0x80003d80,0x3d553d0e,0x3d6dbcc4,0x3c48bd7b,0x3d35bd35,0xbc48bd7b,0xbd6dbcc4,0xbd553d0e,0xbd800000,0xbd0e3d55,0x3cc43d6d,0x3d7b3c48,
0x3d353d35,0x3d7bbc48,0x3cc4bd6d,0xbd0ebd55,0x8000bd80,0xbd55bd0e,0xbd6d3cc4,0xbc483d7b,0xbd353d35,0x3c483d7b,0x3d6d3cc4,0x3d55bd0e,0x3d800000,0x3d0ebd55,0xbcc4bd6d,0xbd7bbc48,
0xbd800000,0xbd353d35,0x80003d80,0x3d353d35,0x3d800000,0x3d35bd35,0x8000bd80,0xbd35bd35,0xbd800000,0xbd353d35,0x80003d80,0x3d353d35,0x3d800000,0x3d35bd35,0x8000bd80,0xbd35bd35,
0xbd800000,0xbd353d35,0x80003d80,0x3d353d35,0x3d800000,0x3d35bd35,0x8000bd80,0xbd35bd35,0xbd800000,0xbd353d35,0x80003d80,0x3d353d35,0x3d800000,0x3d35bd35,0x8000bd80,0xbd35bd35,
0xbd35bd35,0xbd7bbc48,0xbd6d3cc4,0xbd0e3d55,0x3d800000,0x3d55bd0e,0x3cc4bd6d,0xbc48bd7b,0x3d35bd35,0x3c48bd7b,0xbcc4bd6d,0xbd55bd0e,0x80003d80,0x3d0e3d55,0x3d6d3cc4,0x3d7bbc48,
0x3d353d35,0x3d7b3c48,0x3d6dbcc4,0x3d0ebd55,0xbd800000,0xbd553d0e,0xbcc43d6d,0x3c483d7b,0xbd353d35,0xbc483d7b,0x3cc43d6d,0x3d553d0e,0x8000bd80,0xbd0ebd55,0xbd6dbcc4,0xbd7b3c48,
0x3d800000,0x3d6dbcc4,0x3d35bd35,0x3cc4bd6d,0x8000bd80,0xbcc4bd6d,0xbd35bd35,0xbd6dbcc4,0xbd800000,0xbd6d3cc4,0xbd353d35,0xbcc43d6d,0x80003d80,0x3cc43d6d,0x3d353d35,0x3d6d3cc4,
0x3d800000,0x3d6dbcc4,0x3d35bd35,0x3cc4bd6d,0x8000bd80,0xbcc4bd6d,0xbd35bd35,0xbd6dbcc4,0xbd800000,0xbd6d3cc4,0xbd353d35,0xbcc43d6d,0x80003d80,0x3cc43d6d,0x3d353d35,0x3d6d3cc4,
0xbd35bd35,0xbd55bd0e,0xbd6dbcc4,0xbd7bbc48,0x8000bd80,0xbc48bd7b,0xbcc4bd6d,0xbd0ebd55,0x3d35bd35,0x3d0ebd55,0x3cc4bd6d,0x3c48bd7b,0x3d800000,0x3d7bbc48,0x3d6dbcc4,0x3d55bd0e,
0x3d353d35,0x3d553d0e,0x3d6d3cc4,0x3d7b3c48,0x80003d80,0x3c483d7b,0x3cc43d6d,0x3d0e3d55,0xbd353d35,0xbd0e3d55,0xbcc43d6d,0xbc483d7b,0xbd800000,0xbd7b3c48,0xbd6d3cc4,0xbd553d0e,
0x3d80,0xbb493d80,0xbbc93d7f,0xbc163d7d,0xbc483d7b,0xbc793d78,0xbc953d75,0xbcac3d71,0xbcc43d6d,0xbcdb3d67,0xbcf13d62,0xbd043d5c,0xbd0e3d55,0xbd183d4e,0xbd223d46,0xbd2c3d3e,
0xbd353d35,0xbd3e3d2c,0xbd463d22,0xbd4e3d18,0xbd553d0e,0xbd5c3d04,0xbd623cf1,0xbd673cdb,0xbd6d3cc4,0xbd713cac,0xbd753c95,0xbd783c79,0xbd7b3c48,0xbd7d3c16,0xbd7f3bc9,0xbd803b49,
0xbd553d0e,0xbd713cac,0xbd7f3bc9,0xbd7dbc16,0x3d80,0xbc793d78,0xbcf13d62,0xbd2c3d3e,0xbc48bd7b,0x3b49bd80,0x3c95bd75,0x3d04bd5c,0xbd6dbcc4,0xbd4ebd18,0xbd22bd46,0xbcdbbd67,
0x3d7b3c48,0x3d673cdb,0x3d463d22,0x3d183d4e,0x3d35bd35,0x3d5cbd04,0x3d75bc95,0x3d80bb49,0xbd0e3d55,0xbd3e3d2c,0xbd623cf1,0xbd783c79,0x3cc43d6d,0x3c163d7d,0xbbc93d7f,0xbcac3d71,
0x3cc4bd6d,0x3d3ebd2c,0x3d75bc95,0x3d7d3c16,0x3d553d0e,0x3d043d5c,0x3bc93d7f,0xbcac3d71,0x3d80,0xbcdb3d67,0xbd463d22,0xbd783c79,0xbd7bbc48,0xbd4ebd18,0xbcf1bd62,0xbb49bd80,
0x3d6dbcc4,0x3d803b49,0x3d623cf1,0x3d183d4e,0x3c483d7b,0xbc793d78,0xbd223d46,0xbd673cdb,0xbd353d35,0xbd713cac,0xbd7fbbc9,0xbd5cbd04,0xbd0ebd55,0xbc16bd7d,0x3c95bd75,0x3d2cbd3e,
0xbd7b3c48,0xbd67bcdb,0xbcf1bd62,0x3c16bd7d,0x3d6d3cc4,0x3d043d5c,0xbbc93d7f,0xbd2c3d3e,0xbd0ebd55,0x3b49bd80,0x3d22bd46,0x3d78bc79,0x3d80,0xbd183d4e,0xbd753c95,0xbd71bcac,
0x3d553d0e,0x3cac3d71,0xbc953d75,0xbd4e3d18,0xbcc4bd6d,0x3c79bd78,0x3d46bd22,0x3d80bb49,0xbc483d7b,0xbd3e3d2c,0xbd7f3bc9,0xbd5cbd04,0x3d35bd35,0x3d7dbc16,0x3d623cf1,0x3cdb3d67,
0xbd353d35,0xbd80bb49,0xbd22bd46,0x3c16bd7d,0x3d55bd0e,0x3d783c79,0x3cf13d62,0xbcac3d71,0xbd6d3cc4,0xbd67bcdb,0xbc95bd75,0x3d04bd5c,0x3d7bbc48,0x3d4e3d18,0x3bc93d7f,0xbd2c3d3e,
0x3d80,0xbd3e3d2c,0xbd7fbbc9,0xbd18bd4e,0x3c48bd7b,0x3d5cbd04,0x3d753c95,0x3cdb3d67,0xbcc43d6d,0xbd713cac,0xbd62bcf1,0xbc79bd78,0x3d0ebd55,0x3d7dbc16,0x3d463d22,0x3b493d80,
0xbd7bbc48,0xbcacbd71,0x3d22bd46,0x3d7d3c16,0x3d35bd35,0x3d783c79,0x3c953d75,0xbd2c3d3e,0x3d0ebd55,0x3d803b49,0x3cf13d62,0xbd043d5c,0x3cc43d6d,0xbd183d4e,0xbd7fbbc9,0xbcdbbd67,
0x3d55bd0e,0x3d673cdb,0x3bc93d7f,0xbd4e3d18,0x3d80,0xbd5c3d04,0xbd62bcf1,0xbb49bd80,0x3c483d7b,0xbd3e3d2c,0xbd75bc95,0xbc79bd78,0xbd6dbcc4,0xbc16bd7d,0x3d46bd22,0x3d713cac,
0x3d6dbcc4,0x3d2c3d3e,0xbcf13d62,0xbd7dbc16,0xbc48bd7b,0x3d5cbd04,0x3d463d22,0xbcac3d71,0xbd353d35,0xbd67bcdb,0x3bc9bd7f,0x3d78bc79,0x3d0e3d55,0xbd183d4e,0xbd75bc95,0xbb49bd80,
0x3cc4bd6d,0x3d803b49,0x3c953d75,0xbd4e3d18,0xbd55bd0e,0x3c79bd78,0x3d7fbbc9,0x3cdb3d67,0x3d80,0xbd713cac,0xbd22bd46,0x3d04bd5c,0x3d7b3c48,0x3c163d7d,0xbd623cf1,0xbd3ebd2c,
0xbd55bd0e,0x3cdbbd67,0x3d753c95,0xbc163d7d,0xbcc4bd6d,0x3d5cbd04,0x3d223d46,0xbd2c3d3e,0x3c48bd7b,0x3d803b49,0x3bc93d7f,0xbd783c79,0x3d35bd35,0x3d4e3d18,0xbcf13d62,0xbd71bcac,
0x3d7bbc48,0x3cac3d71,0xbd623cf1,0xbd18bd4e,0x3d6d3cc4,0xbc793d78,0xbd7fbbc9,0xbb49bd80,0x3d0e3d55,0xbd3e3d2c,0xbd46bd22,0x3d04bd5c,0x3d80,0xbd7d3c16,0xbc95bd75,0x3d67bcdb,
0xbd800000,0xbd80bb49,0xbd7fbbc9,0xbd7dbc16,0xbd7bbc48,0xbd78bc79,0xbd75bc95,0xbd71bcac,0xbd6dbcc4,0xbd67bcdb,0xbd62bcf1,0xbd5cbd04,0xbd55bd0e,0xbd4ebd18,0xbd46bd22,0xbd3ebd2c,
0xbd35bd35,0xbd2cbd3e,0xbd22bd46,0xbd18bd4e,0xbd0ebd55,0xbd04bd5c,0xbcf1bd62,0xbcdbbd67,0xbcc4bd6d,0xbcacbd71,0xbc95bd75,0xbc79bd78,0xbc48bd7b,0xbc16bd7d,0xbbc9bd7f,0xbb49bd80,
0xbd0ebd55,0xbcacbd71,0xbbc9bd7f,0x3c16bd7d,0xbd800000,0xbd78bc79,0xbd62bcf1,0xbd3ebd2c,0x3d7bbc48,0x3d803b49,0x3d753c95,0x3d5c3d04,0x3cc4bd6d,0x3d18bd4e,0x3d46bd22,0x3d67bcdb,
0xbc483d7b,0xbcdb3d67,0xbd223d46,0xbd4e3d18,0x3d353d35,0x3d043d5c,0x3c953d75,0x3b493d80,0xbd55bd0e,0xbd2cbd3e,0xbcf1bd62,0xbc79bd78,0xbd6d3cc4,0xbd7d3c16,0xbd7fbbc9,0xbd71bcac,
0x3d6d3cc4,0x3d2c3d3e,0x3c953d75,0xbc163d7d,0xbd0e3d55,0xbd5c3d04,0xbd7f3bc9,0xbd71bcac,0xbd800000,0xbd67bcdb,0xbd22bd46,0xbc79bd78,0x3c48bd7b,0x3d18bd4e,0x3d62bcf1,0x3d80bb49,
0x3cc43d6d,0xbb493d80,0xbcf13d62,0xbd4e3d18,0xbd7b3c48,0xbd78bc79,0xbd46bd22,0xbcdbbd67,0xbd35bd35,0xbcacbd71,0x3bc9bd7f,0x3d04bd5c,0x3d55bd0e,0x3d7dbc16,0x3d753c95,0x3d3e3d2c,
0xbc48bd7b,0x3cdbbd67,0x3d62bcf1,0x3d7d3c16,0xbcc43d6d,0xbd5c3d04,0xbd7fbbc9,0xbd3ebd2c,0x3d55bd0e,0x3d803b49,0x3d463d22,0x3c793d78,0xbd800000,0xbd4ebd18,0xbc95bd75,0x3cacbd71,
0xbd0e3d55,0xbd713cac,0xbd75bc95,0xbd18bd4e,0x3d6dbcc4,0x3d783c79,0x3d223d46,0x3b493d80,0xbd7bbc48,0xbd2cbd3e,0xbbc9bd7f,0x3d04bd5c,0x3d353d35,0x3c163d7d,0xbcf13d62,0xbd673cdb,
0xbd35bd35,0x3b49bd80,0x3d46bd22,0x3d7d3c16,0x3d0e3d55,0xbc793d78,0xbd623cf1,0xbd71bcac,0xbcc4bd6d,0x3cdbbd67,0x3d75bc95,0x3d5c3d04,0x3c483d7b,0xbd183d4e,0xbd7f3bc9,0xbd3ebd2c,
0xbd800000,0xbd2cbd3e,0x3bc9bd7f,0x3d4ebd18,0x3d7b3c48,0x3d043d5c,0xbc953d75,0xbd673cdb,0xbd6dbcc4,0xbcacbd71,0x3cf1bd62,0x3d78bc79,0x3d553d0e,0x3c163d7d,0xbd223d46,0xbd803b49,
0x3c48bd7b,0x3d71bcac,0x3d463d22,0xbc163d7d,0x3d353d35,0xbc793d78,0xbd753c95,0xbd3ebd2c,0x3d553d0e,0xbb493d80,0xbd623cf1,0xbd5cbd04,0xbd6d3cc4,0xbd4ebd18,0x3bc9bd7f,0x3d67bcdb,
0x3d0e3d55,0xbcdb3d67,0xbd7f3bc9,0xbd18bd4e,0xbd800000,0xbd04bd5c,0x3cf1bd62,0x3d80bb49,0xbd7b3c48,0xbd2cbd3e,0x3c95bd75,0x3d78bc79,0x3cc4bd6d,0x3d7dbc16,0x3d223d46,0xbcac3d71,
0x3cc43d6d,0xbd3e3d2c,0xbd62bcf1,0x3c16bd7d,0x3d7bbc48,0x3d043d5c,0xbd223d46,0xbd71bcac,0xbd35bd35,0x3cdbbd67,0x3d7f3bc9,0x3c793d78,0xbd553d0e,0xbd4ebd18,0x3c95bd75,0x3d80bb49,
0x3d6d3cc4,0xbb493d80,0xbd753c95,0xbd18bd4e,0x3d0ebd55,0x3d783c79,0x3bc93d7f,0xbd673cdb,0xbd800000,0xbcacbd71,0x3d46bd22,0x3d5c3d04,0xbc483d7b,0xbd7d3c16,0xbcf1bd62,0x3d2cbd3e,
0x3d0ebd55,0x3d673cdb,0xbc953d75,0xbd7dbc16,0x3d6dbcc4,0x3d043d5c,0xbd463d22,0xbd3ebd2c,0x3d7b3c48,0xbb493d80,0xbd7f3bc9,0xbc79bd78,0x3d353d35,0xbd183d4e,0xbd62bcf1,0x3cacbd71,
0x3c483d7b,0xbd713cac,0xbcf1bd62,0x3d4ebd18,0xbcc43d6d,0xbd78bc79,0x3bc9bd7f,0x3d80bb49,0xbd553d0e,0xbd2cbd3e,0x3d22bd46,0x3d5c3d04,0xbd800000,0xbc16bd7d,0x3d75bc95,0x3cdb3d67,
0x3d80,0xbd80bb49,0x3bc9bd7f,0x3d7d3c16,0xbc483d7b,0xbd78bc79,0x3c95bd75,0x3d713cac,0xbcc43d6d,0xbd67bcdb,0x3cf1bd62,0x3d5c3d04,0xbd0e3d55,0xbd4ebd18,0x3d22bd46,0x3d3e3d2c,
0xbd353d35,0xbd2cbd3e,0x3d46bd22,0x3d183d4e,0xbd553d0e,0xbd04bd5c,0x3d62bcf1,0x3cdb3d67,0xbd6d3cc4,0xbcacbd71,0x3d75bc95,0x3c793d78,0xbd7b3c48,0xbc16bd7d,0x3d7fbbc9,0x3b493d80,
0xbd553d0e,0xbcacbd71,0x3d7fbbc9,0xbc163d7d,0x3d80,0xbd78bc79,0x3cf1bd62,0x3d3e3d2c,0xbc48bd7b,0x3d803b49,0xbc953d75,0xbd5cbd04,0xbd6dbcc4,0x3d18bd4e,0x3d223d46,0xbd673cdb,
0x3d7b3c48,0xbcdb3d67,0xbd46bd22,0x3d4ebd18,0x3d35bd35,0x3d043d5c,0xbd753c95,0xbb49bd80,0xbd0e3d55,0xbd2cbd3e,0x3d62bcf1,0x3c793d78,0x3cc43d6d,0xbd7d3c16,0x3bc9bd7f,0x3d713cac,
0x3cc4bd6d,0x3d2c3d3e,0xbd753c95,0x3c16bd7d,0x3d553d0e,0xbd5c3d04,0xbbc9bd7f,0x3d713cac,0x3d80,0xbd67bcdb,0x3d46bd22,0x3c793d78,0xbd7bbc48,0x3d18bd4e,0x3cf13d62,0xbd803b49,
0x3d6dbcc4,0xbb493d80,0xbd62bcf1,0x3d4ebd18,0x3c483d7b,0xbd78bc79,0x3d22bd46,0x3cdb3d67,0xbd353d35,0xbcacbd71,0x3d7f3bc9,0xbd043d5c,0xbd0ebd55,0x3d7dbc16,0xbc953d75,0xbd3ebd2c,
0xbd7b3c48,0x3cdbbd67,0x3cf13d62,0xbd7dbc16,0x3d6d3cc4,0xbd5c3d04,0x3bc9bd7f,0x3d3e3d2c,0xbd0ebd55,0x3d803b49,0xbd223d46,0xbc79bd78,0x3d80,0xbd4ebd18,0x3d75bc95,0xbcac3d71,
0x3d553d0e,0xbd713cac,0x3c95bd75,0x3d183d4e,0xbcc4bd6d,0x3d783c79,0xbd463d22,0xbb49bd80,0xbc483d7b,0xbd2cbd3e,0x3d7fbbc9,0xbd043d5c,0x3d35bd35,0x3c163d7d,0xbd62bcf1,0x3d67bcdb,
0xbd353d35,0x3b49bd80,0x3d223d46,0xbd7dbc16,0x3d55bd0e,0xbc793d78,0xbcf1bd62,0x3d713cac,0xbd6d3cc4,0x3cdbbd67,0x3c953d75,0xbd5cbd04,0x3d7bbc48,0xbd183d4e,0xbbc9bd7f,0x3d3e3d2c,
0x3d80,0xbd2cbd3e,0x3d7f3bc9,0xbd4e3d18,0x3c48bd7b,0x3d043d5c,0xbd75bc95,0x3d67bcdb,0xbcc43d6d,0xbcacbd71,0x3d623cf1,0xbd783c79,0x3d0ebd55,0x3c163d7d,0xbd46bd22,0x3d80bb49,
0xbd7bbc48,0x3d71bcac,0xbd223d46,0x3c16bd7d,0x3d35bd35,0xbc793d78,0xbc95bd75,0x3d3e3d2c,0x3d0ebd55,0xbb493d80,0xbcf1bd62,0x3d5c3d04,0x3cc43d6d,0xbd4ebd18,0x3d7f3bc9,0xbd673cdb,
0x3d55bd0e,0xbcdb3d67,0xbbc9bd7f,0x3d183d4e,0x3d80,0xbd04bd5c,0x3d623cf1,0xbd803b49,0x3c483d7b,0xbd2cbd3e,0x3d753c95,0xbd783c79,0xbd6dbcc4,0x3d7dbc16,0xbd463d22,0x3cacbd71,
0x3d6dbcc4,0xbd3e3d2c,0x3cf1bd62,0xbc163d7d,0xbc48bd7b,0x3d043d5c,0xbd46bd22,0x3d713cac,0xbd353d35,0x3cdbbd67,0xbbc93d7f,0xbc79bd78,0x3d0e3d55,0xbd4ebd18,0x3d753c95,0xbd803b49,
0x3cc4bd6d,0xbb493d80,0xbc95bd75,0x3d183d4e,0xbd55bd0e,0x3d783c79,0xbd7f3bc9,0x3d67bcdb,0x3d80,0xbcacbd71,0x3d223d46,0xbd5cbd04,0x3d7b3c48,0xbd7d3c16,0x3d62bcf1,0xbd2c3d3e,
0xbd55bd0e,0x3d673cdb,0xbd75bc95,0x3d7d3c16,0xbcc4bd6d,0x3d043d5c,0xbd22bd46,0x3d3e3d2c,0x3c48bd7b,0xbb493d80,0xbbc9bd7f,0x3c793d78,0x3d35bd35,0xbd183d4e,0x3cf1bd62,0xbcac3d71,
0x3d7bbc48,0xbd713cac,0x3d62bcf1,0xbd4e3d18,0x3d6d3cc4,0xbd78bc79,0x3d7f3bc9,0xbd803b49,0x3d0e3d55,0xbd2cbd3e,0x3d463d22,0xbd5cbd04,0x3d80,0xbc16bd7d,0x3c953d75,0xbcdbbd67,
0xbd800000,0x3b49bd80,0x3d7f3bc9,0xbc163d7d,0xbd7bbc48,0x3c79bd78,0x3d753c95,0xbcac3d71,0xbd6dbcc4,0x3cdbbd67,0x3d623cf1,0xbd043d5c,0xbd55bd0e,0x3d18bd4e,0x3d463d22,0xbd2c3d3e,
0xbd35bd35,0x3d3ebd2c,0x3d223d46,0xbd4e3d18,0xbd0ebd55,0x3d5cbd04,0x3cf13d62,0xbd673cdb,0xbcc4bd6d,0x3d71bcac,0x3c953d75,0xbd783c79,0xbc48bd7b,0x3d7dbc16,0x3bc93d7f,0xbd803b49,
0xbd0ebd55,0x3d71bcac,0x3bc93d7f,0xbd7dbc16,0xbd800000,0x3c79bd78,0x3d623cf1,0xbd2c3d3e,0x3d7bbc48,0xbb493d80,0xbd75bc95,0x3d04bd5c,0x3cc4bd6d,0x3d4e3d18,0xbd463d22,0xbcdbbd67,
0xbc483d7b,0xbd67bcdb,0x3d22bd46,0x3d183d4e,0x3d353d35,0xbd5c3d04,0xbc95bd75,0x3d80bb49,0xbd55bd0e,0x3d3ebd2c,0x3cf13d62,0xbd783c79,0xbd6d3cc4,0xbc16bd7d,0x3d7f3bc9,0xbcac3d71,
0x3d6d3cc4,0xbd3e3d2c,0xbc95bd75,0x3d7d3c16,0xbd0e3d55,0xbd04bd5c,0x3d7fbbc9,0xbcac3d71,0xbd800000,0x3cdbbd67,0x3d223d46,0xbd783c79,0x3c48bd7b,0x3d4e3d18,0xbd623cf1,0xbb49bd80,
0x3cc43d6d,0xbd80bb49,0x3cf1bd62,0x3d183d4e,0xbd7b3c48,0x3c79bd78,0x3d463d22,0xbd673cdb,0xbd35bd35,0x3d71bcac,0xbbc93d7f,0xbd5cbd04,0x3d55bd0e,0x3c163d7d,0xbd75bc95,0x3d2cbd3e,
0xbc48bd7b,0x3d673cdb,0xbd623cf1,0x3c16bd7d,0xbcc43d6d,0xbd04bd5c,0x3d7f3bc9,0xbd2c3d3e,0x3d55bd0e,0xbb493d80,0xbd46bd22,0x3d78bc79,0xbd800000,0x3d18bd4e,0x3c953d75,0xbd71bcac,
0xbd0e3d55,0xbcacbd71,0x3d753c95,0xbd4e3d18,0x3d6dbcc4,0xbc793d78,0xbd22bd46,0x3d80bb49,0xbd7bbc48,0x3d3ebd2c,0x3bc93d7f,0xbd5cbd04,0x3d353d35,0xbd7d3c16,0x3cf1bd62,0x3cdb3d67,
0xbd35bd35,0x3d803b49,0xbd463d22,0x3c16bd7d,0x3d0e3d55,0xbd78bc79,0x3d62bcf1,0xbcac3d71,0xbcc4bd6d,0x3d673cdb,0xbd753c95,0x3d04bd5c,0x3c483d7b,0xbd4ebd18,0x3d7fbbc9,0xbd2c3d3e,
0xbd800000,0x3d3ebd2c,0xbbc93d7f,0xbd18bd4e,0x3d7b3c48,0xbd5c3d04,0x3c95bd75,0x3cdb3d67,0xbd6dbcc4,0x3d71bcac,0xbcf13d62,0xbc79bd78,0x3d553d0e,0xbd7d3c16,0x3d22bd46,0x3b493d80,
0x3c48bd7b,0x3cac3d71,0xbd46bd22,0x3d7d3c16,0x3d353d35,0xbd78bc79,0x3d75bc95,0xbd2c3d3e,0x3d553d0e,0xbd80bb49,0x3d62bcf1,0xbd043d5c,0xbd6d3cc4,0x3d18bd4e,0xbbc93d7f,0xbcdbbd67,
0x3d0e3d55,0xbd67bcdb,0x3d7fbbc9,0xbd4e3d18,0xbd800000,0x3d5cbd04,0xbcf13d62,0xbb49bd80,0xbd7b3c48,0x3d3ebd2c,0xbc953d75,0xbc79bd78,0x3cc4bd6d,0x3c163d7d,0xbd22bd46,0x3d713cac,
0x3cc43d6d,0xbd2cbd3e,0x3d623cf1,0xbd7dbc16,0x3d7bbc48,0xbd5c3d04,0x3d22bd46,0xbcac3d71,0xbd35bd35,0x3d673cdb,0xbd7fbbc9,0x3d78bc79,0xbd553d0e,0x3d18bd4e,0xbc953d75,0xbb49bd80,
0x3d6d3cc4,0xbd80bb49,0x3d75bc95,0xbd4e3d18,0x3d0ebd55,0xbc793d78,0xbbc9bd7f,0x3cdb3d67,0xbd800000,0x3d71bcac,0xbd463d22,0x3d04bd5c,0xbc483d7b,0xbc16bd7d,0x3cf13d62,0xbd3ebd2c,
0x3d0ebd55,0xbcdb3d67,0x3c95bd75,0xbc163d7d,0x3d6dbcc4,0xbd5c3d04,0x3d46bd22,0xbd2c3d3e,0x3d7b3c48,0xbd80bb49,0x3d7fbbc9,0xbd783c79,0x3d353d35,0xbd4ebd18,0x3d623cf1,0xbd71bcac,
0x3c483d7b,0xbcacbd71,0x3cf13d62,0xbd18bd4e,0xbcc43d6d,0x3c79bd78,0xbbc93d7f,0xbb49bd80,0xbd553d0e,0x3d3ebd2c,0xbd223d46,0x3d04bd5c,0xbd800000,0x3d7dbc16,0xbd753c95,0x3d67bcdb,
0x3d80,0x3b49bd80,0xbbc93d7f,0x3c16bd7d,0xbc483d7b,0x3c79bd78,0xbc953d75,0x3cacbd71,0xbcc43d6d,0x3cdbbd67,0xbcf13d62,0x3d04bd5c,0xbd0e3d55,0x3d18bd4e,0xbd223d46,0x3d2cbd3e,
0xbd353d35,0x3d3ebd2c,0xbd463d22,0x3d4ebd18,0xbd553d0e,0x3d5cbd04,0xbd623cf1,0x3d67bcdb,0xbd6d3cc4,0x3d71bcac,0xbd753c95,0x3d78bc79,0xbd7b3c48,0x3d7dbc16,0xbd7f3bc9,0x3d80bb49,
0xbd553d0e,0x3d71bcac,0xbd7f3bc9,0x3d7d3c16,0x3d80,0x3c79bd78,0xbcf13d62,0x3d2cbd3e,0xbc48bd7b,0xbb493d80,0x3c95bd75,0xbd043d5c,0xbd6dbcc4,0x3d4e3d18,0xbd22bd46,0x3cdb3d67,
0x3d7b3c48,0xbd67bcdb,0x3d463d22,0xbd18bd4e,0x3d35bd35,0xbd5c3d04,0x3d75bc95,0xbd803b49,0xbd0e3d55,0x3d3ebd2c,0xbd623cf1,0x3d78bc79,0x3cc43d6d,0xbc16bd7d,0xbbc93d7f,0x3cacbd71,
0x3cc4bd6d,0xbd3e3d2c,0x3d75bc95,0xbd7dbc16,0x3d553d0e,0xbd04bd5c,0x3bc93d7f,0x3cacbd71,0x3d80,0x3cdbbd67,0xbd463d22,0x3d78bc79,0xbd7bbc48,0x3d4e3d18,0xbcf1bd62,0x3b493d80,
0x3d6dbcc4,0xbd80bb49,0x3d623cf1,0xbd18bd4e,0x3c483d7b,0x3c79bd78,0xbd223d46,0x3d67bcdb,0xbd353d35,0x3d71bcac,0xbd7fbbc9,0x3d5c3d04,0xbd0ebd55,0x3c163d7d,0x3c95bd75,0xbd2c3d3e,
0xbd7b3c48,0x3d673cdb,0xbcf1bd62,0xbc163d7d,0x3d6d3cc4,0xbd04bd5c,0xbbc93d7f,0x3d2cbd3e,0xbd0ebd55,0xbb493d80,0x3d22bd46,0xbd783c79,0x3d80,0x3d18bd4e,0xbd753c95,0x3d713cac,
0x3d553d0e,0xbcacbd71,0xbc953d75,0x3d4ebd18,0xbcc4bd6d,0xbc793d78,0x3d46bd22,0xbd803b49,0xbc483d7b,0x3d3ebd2c,0xbd7f3bc9,0x3d5c3d04,0x3d35bd35,0xbd7d3c16,0x3d623cf1,0xbcdbbd67,
0xbd353d35,0x3d803b49,0xbd22bd46,0xbc163d7d,0x3d55bd0e,0xbd78bc79,0x3cf13d62,0x3cacbd71,0xbd6d3cc4,0x3d673cdb,0xbc95bd75,0xbd043d5c,0x3d7bbc48,0xbd4ebd18,0x3bc93d7f,0x3d2cbd3e,
0x3d80,0x3d3ebd2c,0xbd7fbbc9,0x3d183d4e,0x3c48bd7b,0xbd5c3d04,0x3d753c95,0xbcdbbd67,0xbcc43d6d,0x3d71bcac,0xbd62bcf1,0x3c793d78,0x3d0ebd55,0xbd7d3c16,0x3d463d22,0xbb49bd80,
0xbd7bbc48,0x3cac3d71,0x3d22bd46,0xbd7dbc16,0x3d35bd35,0xbd78bc79,0x3c953d75,0x3d2cbd3e,0x3d0ebd55,0xbd80bb49,0x3cf13d62,0x3d04bd5c,0x3cc43d6d,0x3d18bd4e,0xbd7fbbc9,0x3cdb3d67,
0x3d55bd0e,0xbd67bcdb,0x3bc93d7f,0x3d4ebd18,0x3d80,0x3d5cbd04,0xbd62bcf1,0x3b493d80,0x3c483d7b,0x3d3ebd2c,0xbd75bc95,0x3c793d78,0xbd6dbcc4,0x3c163d7d,0x3d46bd22,0xbd71bcac,
0x3d6dbcc4,0xbd2cbd3e,0xbcf13d62,0x3d7d3c16,0xbc48bd7b,0xbd5c3d04,0x3d463d22,0x3cacbd71,0xbd353d35,0x3d673cdb,0x3bc9bd7f,0xbd783c79,0x3d0e3d55,0x3d18bd4e,0xbd75bc95,0x3b493d80,
0x3cc4bd6d,0xbd80bb49,0x3c953d75,0x3d4ebd18,0xbd55bd0e,0xbc793d78,0x3d7fbbc9,0xbcdbbd67,0x3d80,0x3d71bcac,0xbd22bd46,0xbd043d5c,0x3d7b3c48,0xbc16bd7d,0xbd623cf1,0x3d3e3d2c,
0xbd55bd0e,0xbcdb3d67,0x3d753c95,0x3c16bd7d,0xbcc4bd6d,0xbd5c3d04,0x3d223d46,0x3d2cbd3e,0x3c48bd7b,0xbd80bb49,0x3bc93d7f,0x3d78bc79,0x3d35bd35,0xbd4ebd18,0xbcf13d62,0x3d713cac,
0x3d7bbc48,0xbcacbd71,0xbd623cf1,0x3d183d4e,0x3d6d3cc4,0x3c79bd78,0xbd7fbbc9,0x3b493d80,0x3d0e3d55,0x3d3ebd2c,0xbd46bd22,0xbd043d5c,0x3d80,0x3d7dbc16,0xbc95bd75,0xbd673cdb,
0xbd800000,0x3d803b49,0xbd7fbbc9,0x3d7d3c16,0xbd7bbc48,0x3d783c79,0xbd75bc95,0x3d713cac,0xbd6dbcc4,0x3d673cdb,0xbd62bcf1,0x3d5c3d04,0xbd55bd0e,0x3d4e3d18,0xbd46bd22,0x3d3e3d2c,
0xbd35bd35,0x3d2c3d3e,0xbd22bd46,0x3d183d4e,0xbd0ebd55,0x3d043d5c,0xbcf1bd62,0x3cdb3d67,0xbcc4bd6d,0x3cac3d71,0xbc95bd75,0x3c793d78,0xbc48bd7b,0x3c163d7d,0xbbc9bd7f,0x3b493d80,
0xbd0ebd55,0x3cac3d71,0xbbc9bd7f,0xbc163d7d,0xbd800000,0x3d783c79,0xbd62bcf1,0x3d3e3d2c,0x3d7bbc48,0xbd80bb49,0x3d753c95,0xbd5cbd04,0x3cc4bd6d,0xbd183d4e,0x3d46bd22,0xbd673cdb,
0xbc483d7b,0x3cdbbd67,0xbd223d46,0x3d4ebd18,0x3d353d35,0xbd04bd5c,0x3c953d75,0xbb49bd80,0xbd55bd0e,0x3d2c3d3e,0xbcf1bd62,0x3c793d78,0xbd6d3cc4,0x3d7dbc16,0xbd7fbbc9,0x3d713cac,
0x3d6d3cc4,0xbd2cbd3e,0x3c953d75,0x3c16bd7d,0xbd0e3d55,0x3d5cbd04,0xbd7f3bc9,0x3d713cac,0xbd800000,0x3d673cdb,0xbd22bd46,0x3c793d78,0x3c48bd7b,0xbd183d4e,0x3d62bcf1,0xbd803b49,
0x3cc43d6d,0x3b49bd80,0xbcf13d62,0x3d4ebd18,0xbd7b3c48,0x3d783c79,0xbd46bd22,0x3cdb3d67,0xbd35bd35,0x3cac3d71,0x3bc9bd7f,0xbd043d5c,0x3d55bd0e,0xbd7d3c16,0x3d753c95,0xbd3ebd2c,
0xbc48bd7b,0xbcdb3d67,0x3d62bcf1,0xbd7dbc16,0xbcc43d6d,0x3d5cbd04,0xbd7fbbc9,0x3d3e3d2c,0x3d55bd0e,0xbd80bb49,0x3d463d22,0xbc79bd78,0xbd800000,0x3d4e3d18,0xbc95bd75,0xbcac3d71,
0xbd0e3d55,0x3d71bcac,0xbd75bc95,0x3d183d4e,0x3d6dbcc4,0xbd78bc79,0x3d223d46,0xbb49bd80,0xbd7bbc48,0x3d2c3d3e,0xbbc9bd7f,0xbd043d5c,0x3d353d35,0xbc16bd7d,0xbcf13d62,0x3d67bcdb,
0xbd35bd35,0xbb493d80,0x3d46bd22,0xbd7dbc16,0x3d0e3d55,0x3c79bd78,0xbd623cf1,0x3d713cac,0xbcc4bd6d,0xbcdb3d67,0x3d75bc95,0xbd5cbd04,0x3c483d7b,0x3d18bd4e,0xbd7f3bc9,0x3d3e3d2c,
0xbd800000,0x3d2c3d3e,0x3bc9bd7f,0xbd4e3d18,0x3d7b3c48,0xbd04bd5c,0xbc953d75,0x3d67bcdb,0xbd6dbcc4,0x3cac3d71,0x3cf1bd62,0xbd783c79,0x3d553d0e,0xbc16bd7d,0xbd223d46,0x3d80bb49,
0x3c48bd7b,0xbd713cac,0x3d463d22,0x3c16bd7d,0x3d353d35,0x3c79bd78,0xbd753c95,0x3d3e3d2c,0x3d553d0e,0x3b49bd80,0xbd623cf1,0x3d5c3d04,0xbd6d3cc4,0x3d4e3d18,0x3bc9bd7f,0xbd673cdb,
0x3d0e3d55,0x3cdbbd67,0xbd7f3bc9,0x3d183d4e,0xbd800000,0x3d043d5c,0x3cf1bd62,0xbd803b49,0xbd7b3c48,0x3d2c3d3e,0x3c95bd75,0xbd783c79,0x3cc4bd6d,0xbd7d3c16,0x3d223d46,0x3cacbd71,
0x3cc43d6d,0x3d3ebd2c,0xbd62bcf1,0xbc163d7d,0x3d7bbc48,0xbd04bd5c,0xbd223d46,0x3d713cac,0xbd35bd35,0xbcdb3d67,0x3d7f3bc9,0xbc79bd78,0xbd553d0e,0x3d4e3d18,0x3c95bd75,0xbd803b49,
0x3d6d3cc4,0x3b49bd80,0xbd753c95,0x3d183d4e,0x3d0ebd55,0xbd78bc79,0x3bc93d7f,0x3d67bcdb,0xbd800000,0x3cac3d71,0x3d46bd22,0xbd5cbd04,0xbc483d7b,0x3d7dbc16,0xbcf1bd62,0xbd2c3d3e,
0x3d0ebd55,0xbd67bcdb,0xbc953d75,0x3d7d3c16,0x3d6dbcc4,0xbd04bd5c,0xbd463d22,0x3d3e3d2c,0x3d7b3c48,0x3b49bd80,0xbd7f3bc9,0x3c793d78,0x3d353d35,0x3d18bd4e,0xbd62bcf1,0xbcac3d71,
0x3c483d7b,0x3d71bcac,0xbcf1bd62,0xbd4e3d18,0xbcc43d6d,0x3d783c79,0x3bc9bd7f,0xbd803b49,0xbd553d0e,0x3d2c3d3e,0x3d22bd46,0xbd5cbd04,0xbd800000,0x3c163d7d,0x3d75bc95,0xbcdbbd67,
0x3d80,0x3d803b49,0x3bc9bd7f,0xbd7dbc16,0xbc483d7b,0x3d783c79,0x3c95bd75,0xbd71bcac,0xbcc43d6d,0x3d673cdb,0x3cf1bd62,0xbd5cbd04,0xbd0e3d55,0x3d4e3d18,0x3d22bd46,0xbd3ebd2c,
0xbd353d35,0x3d2c3d3e,0x3d46bd22,0xbd18bd4e,0xbd553d0e,0x3d043d5c,0x3d62bcf1,0xbcdbbd67,0xbd6d3cc4,0x3cac3d71,0x3d75bc95,0xbc79bd78,0xbd7b3c48,0x3c163d7d,0x3d7fbbc9,0xbb49bd80,
0xbd553d0e,0x3cac3d71,0x3d7fbbc9,0x3c16bd7d,0x3d80,0x3d783c79,0x3cf1bd62,0xbd3ebd2c,0xbc48bd7b,0xbd80bb49,0xbc953d75,0x3d5c3d04,0xbd6dbcc4,0xbd183d4e,0x3d223d46,0x3d67bcdb,
0x3d7b3c48,0x3cdbbd67,0xbd46bd22,0xbd4e3d18,0x3d35bd35,0xbd04bd5c,0xbd753c95,0x3b493d80,0xbd0e3d55,0x3d2c3d3e,0x3d62bcf1,0xbc79bd78,0x3cc43d6d,0x3d7dbc16,0x3bc9bd7f,0xbd71bcac,
0x3cc4bd6d,0xbd2cbd3e,0xbd753c95,0xbc163d7d,0x3d553d0e,0x3d5cbd04,0xbbc9bd7f,0xbd71bcac,0x3d80,0x3d673cdb,0x3d46bd22,0xbc79bd78,0xbd7bbc48,0xbd183d4e,0x3cf13d62,0x3d80bb49,
0x3d6dbcc4,0x3b49bd80,0xbd62bcf1,0xbd4e3d18,0x3c483d7b,0x3d783c79,0x3d22bd46,0xbcdbbd67,0xbd353d35,0x3cac3d71,0x3d7f3bc9,0x3d04bd5c,0xbd0ebd55,0xbd7d3c16,0xbc953d75,0x3d3e3d2c,
0xbd7b3c48,0xbcdb3d67,0x3cf13d62,0x3d7d3c16,0x3d6d3cc4,0x3d5cbd04,0x3bc9bd7f,0xbd3ebd2c,0xbd0ebd55,0xbd80bb49,0xbd223d46,0x3c793d78,0x3d80,0x3d4e3d18,0x3d75bc95,0x3cacbd71,
0x3d553d0e,0x3d71bcac,0x3c95bd75,0xbd18bd4e,0xbcc4bd6d,0xbd78bc79,0xbd463d22,0x3b493d80,0xbc483d7b,0x3d2c3d3e,0x3d7fbbc9,0x3d04bd5c,0x3d35bd35,0xbc16bd7d,0xbd62bcf1,0xbd673cdb,
0xbd353d35,0xbb493d80,0x3d223d46,0x3d7d3c16,0x3d55bd0e,0x3c79bd78,0xbcf1bd62,0xbd71bcac,0xbd6d3cc4,0xbcdb3d67,0x3c953d75,0x3d5c3d04,0x3d7bbc48,0x3d18bd4e,0xbbc9bd7f,0xbd3ebd2c,
0x3d80,0x3d2c3d3e,0x3d7f3bc9,0x3d4ebd18,0x3c48bd7b,0xbd04bd5c,0xbd75bc95,0xbd673cdb,0xbcc43d6d,0x3cac3d71,0x3d623cf1,0x3d78bc79,0x3d0ebd55,0xbc16bd7d,0xbd46bd22,0xbd803b49,
0xbd7bbc48,0xbd713cac,0xbd223d46,0xbc163d7d,0x3d35bd35,0x3c79bd78,0xbc95bd75,0xbd3ebd2c,0x3d0ebd55,0x3b49bd80,0xbcf1bd62,0xbd5cbd04,0x3cc43d6d,0x3d4e3d18,0x3d7f3bc9,0x3d67bcdb,
0x3d55bd0e,0x3cdbbd67,0xbbc9bd7f,0xbd18bd4e,0x3d80,0x3d043d5c,0x3d623cf1,0x3d80bb49,0x3c483d7b,0x3d2c3d3e,0x3d753c95,0x3d78bc79,0xbd6dbcc4,0xbd7d3c16,0xbd463d22,0xbcac3d71,
0x3d6dbcc4,0x3d3ebd2c,0x3cf1bd62,0x3c16bd7d,0xbc48bd7b,0xbd04bd5c,0xbd46bd22,0xbd71bcac,0xbd353d35,0xbcdb3d67,0xbbc93d7f,0x3c793d78,0x3d0e3d55,0x3d4e3d18,0x3d753c95,0x3d80bb49,
0x3cc4bd6d,0x3b49bd80,0xbc95bd75,0xbd18bd4e,0xbd55bd0e,0xbd78bc79,0xbd7f3bc9,0xbd673cdb,0x3d80,0x3cac3d71,0x3d223d46,0x3d5c3d04,0x3d7b3c48,0x3d7dbc16,0x3d62bcf1,0x3d2cbd3e,
0xbd55bd0e,0xbd67bcdb,0xbd75bc95,0xbd7dbc16,0xbcc4bd6d,0xbd04bd5c,0xbd22bd46,0xbd3ebd2c,0x3c48bd7b,0x3b49bd80,0xbbc9bd7f,0xbc79bd78,0x3d35bd35,0x3d18bd4e,0x3cf1bd62,0x3cacbd71,
0x3d7bbc48,0x3d71bcac,0x3d62bcf1,0x3d4ebd18,0x3d6d3cc4,0x3d783c79,0x3d7f3bc9,0x3d80bb49,0x3d0e3d55,0x3d2c3d3e,0x3d463d22,0x3d5c3d04,0x3d80,0x3c163d7d,0x3c953d75,0x3cdb3d67,
0xbd800000,0xbb493d80,0x3d7f3bc9,0x3c16bd7d,0xbd7bbc48,0xbc793d78,0x3d753c95,0x3cacbd71,0xbd6dbcc4,0xbcdb3d67,0x3d623cf1,0x3d04bd5c,0xbd55bd0e,0xbd183d4e,0x3d463d22,0x3d2cbd3e,
0xbd35bd35,0xbd3e3d2c,0x3d223d46,0x3d4ebd18,0xbd0ebd55,0xbd5c3d04,0x3cf13d62,0x3d67bcdb,0xbcc4bd6d,0xbd713cac,0x3c953d75,0x3d78bc79,0xbc48bd7b,0xbd7d3c16,0x3bc93d7f,0x3d80bb49,
0xbd0ebd55,0xbd713cac,0x3bc93d7f,0x3d7d3c16,0xbd800000,0xbc793d78,0x3d623cf1,0x3d2cbd3e,0x3d7bbc48,0x3b49bd80,0xbd75bc95,0xbd043d5c,0x3cc4bd6d,0xbd4ebd18,0xbd463d22,0x3cdb3d67,
0xbc483d7b,0x3d673cdb,0x3d22bd46,0xbd18bd4e,0x3d353d35,0x3d5cbd04,0xbc95bd75,0xbd803b49,0xbd55bd0e,0xbd3e3d2c,0x3cf13d62,0x3d78bc79,0xbd6d3cc4,0x3c163d7d,0x3d7f3bc9,0x3cacbd71,
0x3d6d3cc4,0x3d3ebd2c,0xbc95bd75,0xbd7dbc16,0xbd0e3d55,0x3d043d5c,0x3d7fbbc9,0x3cacbd71,0xbd800000,0xbcdb3d67,0x3d223d46,0x3d78bc79,0x3c48bd7b,0xbd4ebd18,0xbd623cf1,0x3b493d80,
0x3cc43d6d,0x3d803b49,0x3cf1bd62,0xbd18bd4e,0xbd7b3c48,0xbc793d78,0x3d463d22,0x3d67bcdb,0xbd35bd35,0xbd713cac,0xbbc93d7f,0x3d5c3d04,0x3d55bd0e,0xbc16bd7d,0xbd75bc95,0xbd2c3d3e,
0xbc48bd7b,0xbd67bcdb,0xbd623cf1,0xbc163d7d,0xbcc43d6d,0x3d043d5c,0x3d7f3bc9,0x3d2cbd3e,0x3d55bd0e,0x3b49bd80,0xbd46bd22,0xbd783c79,0xbd800000,0xbd183d4e,0x3c953d75,0x3d713cac,
0xbd0e3d55,0x3cac3d71,0x3d753c95,0x3d4ebd18,0x3d6dbcc4,0x3c79bd78,0xbd22bd46,0xbd803b49,0xbd7bbc48,0xbd3e3d2c,0x3bc93d7f,0x3d5c3d04,0x3d353d35,0x3d7dbc16,0x3cf1bd62,0xbcdbbd67,
0xbd35bd35,0xbd80bb49,0xbd463d22,0xbc163d7d,0x3d0e3d55,0x3d783c79,0x3d62bcf1,0x3cacbd71,0xbcc4bd6d,0xbd67bcdb,0xbd753c95,0xbd043d5c,0x3c483d7b,0x3d4e3d18,0x3d7fbbc9,0x3d2cbd3e,
0xbd800000,0xbd3e3d2c,0xbbc93d7f,0x3d183d4e,0x3d7b3c48,0x3d5cbd04,0x3c95bd75,0xbcdbbd67,0xbd6dbcc4,0xbd713cac,0xbcf13d62,0x3c793d78,0x3d553d0e,0x3d7dbc16,0x3d22bd46,0xbb49bd80,
0x3c48bd7b,0xbcacbd71,0xbd46bd22,0xbd7dbc16,0x3d353d35,0x3d783c79,0x3d75bc95,0x3d2cbd3e,0x3d553d0e,0x3d803b49,0x3d62bcf1,0x3d04bd5c,0xbd6d3cc4,0xbd183d4e,0xbbc93d7f,0x3cdb3d67,
0x3d0e3d55,0x3d673cdb,0x3d7fbbc9,0x3d4ebd18,0xbd800000,0xbd5c3d04,0xbcf13d62,0x3b493d80,0xbd7b3c48,0xbd3e3d2c,0xbc953d75,0x3c793d78,0x3cc4bd6d,0xbc16bd7d,0xbd22bd46,0xbd71bcac,
0x3cc43d6d,0x3d2c3d3e,0x3d623cf1,0x3d7d3c16,0x3d7bbc48,0x3d5cbd04,0x3d22bd46,0x3cacbd71,0xbd35bd35,0xbd67bcdb,0xbd7fbbc9,0xbd783c79,0xbd553d0e,0xbd183d4e,0xbc953d75,0x3b493d80,
0x3d6d3cc4,0x3d803b49,0x3d75bc95,0x3d4ebd18,0x3d0ebd55,0x3c79bd78,0xbbc9bd7f,0xbcdbbd67,0xbd800000,0xbd713cac,0xbd463d22,0xbd043d5c,0xbc483d7b,0x3c163d7d,0x3cf13d62,0x3d3e3d2c,
0x3d0ebd55,0x3cdbbd67,0x3c95bd75,0x3c16bd7d,0x3d6dbcc4,0x3d5cbd04,0x3d46bd22,0x3d2cbd3e,0x3d7b3c48,0x3d803b49,0x3d7fbbc9,0x3d78bc79,0x3d353d35,0x3d4e3d18,0x3d623cf1,0x3d713cac,
0x3c483d7b,0x3cac3d71,0x3cf13d62,0x3d183d4e,0xbcc43d6d,0xbc793d78,0xbbc93d7f,0x3b493d80,0xbd553d0e,0xbd3e3d2c,0xbd223d46,0xbd043d5c,0xbd800000,0xbd7d3c16,0xbd753c95,0xbd673cdb,
0x3d80,0xbbc93d7f,0xbc483d7b,0xbc953d75,0xbcc43d6d,0xbcf13d62,0xbd0e3d55,0xbd223d46,0xbd353d35,0xbd463d22,0xbd553d0e,0xbd623cf1,0xbd6d3cc4,0xbd753c95,0xbd7b3c48,0xbd7f3bc9,
0xbd800000,0xbd7fbbc9,0xbd7bbc48,0xbd75bc95,0xbd6dbcc4,0xbd62bcf1,0xbd55bd0e,0xbd46bd22,0xbd35bd35,0xbd22bd46,0xbd0ebd55,0xbcf1bd62,0xbcc4bd6d,0xbc95bd75,0xbc48bd7b,0xbbc9bd7f,
0xbd6d3cc4,0xbd7f3bc9,0xbd7bbc48,0xbd62bcf1,0x3d80,0xbc953d75,0xbd0e3d55,0xbd463d22,0x3cc4bd6d,0x3d22bd46,0x3d55bd0e,0x3d75bc95,0xbd35bd35,0xbcf1bd62,0xbc48bd7b,0x3bc9bd7f,
0x3cc43d6d,0x3bc93d7f,0xbc483d7b,0xbcf13d62,0x3d800000,0x3d753c95,0x3d553d0e,0x3d223d46,0xbd6dbcc4,0xbd46bd22,0xbd0ebd55,0xbc95bd75,0xbd353d35,0xbd623cf1,0xbd7b3c48,0xbd7fbbc9,
0x3d35bd35,0x3d75bc95,0x3d7b3c48,0x3d463d22,0x3cc43d6d,0xbbc93d7f,0xbd0e3d55,0xbd623cf1,0x3d80,0xbcf13d62,0xbd553d0e,0xbd7f3bc9,0xbd6dbcc4,0xbd22bd46,0xbc48bd7b,0x3c95bd75,
0x3d353d35,0x3c953d75,0xbc483d7b,0xbd223d46,0xbd6d3cc4,0xbd7fbbc9,0xbd55bd0e,0xbcf1bd62,0xbd800000,0xbd62bcf1,0xbd0ebd55,0xbbc9bd7f,0x3cc4bd6d,0x3d46bd22,0x3d7bbc48,0x3d753c95,
0xbd6dbcc4,0xbcf1bd62,0x3c48bd7b,0x3d46bd22,0x3d353d35,0x3bc93d7f,0xbd0e3d55,0xbd753c95,0xbcc4bd6d,0x3c95bd75,0x3d55bd0e,0x3d7f3bc9,0x3d80,0xbd223d46,0xbd7b3c48,0xbd62bcf1,
0xbcc43d6d,0xbd623cf1,0xbd7bbc48,0xbd22bd46,0x3d35bd35,0x3d7fbbc9,0x3d553d0e,0x3c953d75,0xbd6d3cc4,0xbd75bc95,0xbd0ebd55,0x3bc9bd7f,0x3d800000,0x3d463d22,0x3c483d7b,0xbcf13d62,
0xbd800000,0xbd22bd46,0x3c48bd7b,0x3d62bcf1,0x3d6d3cc4,0x3c953d75,0xbd0e3d55,0xbd7f3bc9,0xbd35bd35,0x3bc9bd7f,0x3d55bd0e,0x3d753c95,0x3cc43d6d,0xbcf13d62,0xbd7b3c48,0xbd46bd22,
0x3d80,0xbd463d22,0xbd7bbc48,0xbcf1bd62,0x3cc4bd6d,0x3d75bc95,0x3d553d0e,0x3bc93d7f,0xbd353d35,0xbd7fbbc9,0xbd0ebd55,0x3c95bd75,0x3d6dbcc4,0x3d623cf1,0x3c483d7b,0xbd223d46,
0xbcc4bd6d,0x3d22bd46,0x3d7b3c48,0x3c953d75,0x3d800000,0x3cf13d62,0xbd0e3d55,0xbd7fbbc9,0x3d6d3cc4,0x3bc93d7f,0xbd553d0e,0xbd62bcf1,0xbd353d35,0xbd75bc95,0xbc48bd7b,0x3d46bd22,
0x3d6dbcc4,0x3d463d22,0xbc483d7b,0xbd753c95,0x3d80,0xbd623cf1,0xbd55bd0e,0x3bc9bd7f,0xbcc43d6d,0xbd7f3bc9,0xbd0ebd55,0x3cf1bd62,0xbd35bd35,0x3c95bd75,0x3d7bbc48,0x3d223d46,
0x3d353d35,0xbcf13d62,0xbd7bbc48,0xbbc9bd7f,0x3d6dbcc4,0x3d223d46,0xbd0e3d55,0xbd75bc95,0xbd800000,0xbc95bd75,0x3d55bd0e,0x3d463d22,0xbcc43d6d,0xbd7fbbc9,0xbc48bd7b,0x3d62bcf1,
0x3d35bd35,0x3d623cf1,0xbc483d7b,0xbd7f3bc9,0xbcc4bd6d,0x3d46bd22,0x3d553d0e,0xbc953d75,0x3d80,0xbd753c95,0xbd0ebd55,0x3d22bd46,0x3d6d3cc4,0xbbc93d7f,0xbd7b3c48,0xbcf1bd62,
0x3cc4bd6d,0x3d753c95,0xbc483d7b,0xbd7fbbc9,0x3d35bd35,0x3d463d22,0xbd0e3d55,0xbd62bcf1,0x3d6dbcc4,0x3cf13d62,0xbd553d0e,0xbd22bd46,0x3d800000,0x3bc93d7f,0xbd7b3c48,0xbc95bd75,
0x3d6d3cc4,0xbc953d75,0xbd7bbc48,0x3bc9bd7f,0x3d353d35,0xbd223d46,0xbd55bd0e,0x3cf1bd62,0x3cc43d6d,0xbd623cf1,0xbd0ebd55,0x3d46bd22,0x3d80,0xbd7f3bc9,0xbc48bd7b,0x3d75bc95,
0xbd800000,0xbd7fbbc9,0xbd7bbc48,0xbd75bc95,0xbd6dbcc4,0xbd62bcf1,0xbd55bd0e,0xbd46bd22,0xbd35bd35,0xbd22bd46,0xbd0ebd55,0xbcf1bd62,0xbcc4bd6d,0xbc95bd75,0xbc48bd7b,0xbbc9bd7f,
0x8000bd80,0x3bc9bd7f,0x3c48bd7b,0x3c95bd75,0x3cc4bd6d,0x3cf1bd62,0x3d0ebd55,0x3d22bd46,0x3d35bd35,0x3d46bd22,0x3d55bd0e,0x3d62bcf1,0x3d6dbcc4,0x3d75bc95,0x3d7bbc48,0x3d7fbbc9,
0xbcc4bd6d,0xbbc9bd7f,0x3c48bd7b,0x3cf1bd62,0xbd800000,0xbd75bc95,0xbd55bd0e,0xbd22bd46,0x3d6d3cc4,0x3d463d22,0x3d0e3d55,0x3c953d75,0x3d35bd35,0x3d62bcf1,0x3d7bbc48,0x3d7f3bc9,
0xbd6d3cc4,0xbd7f3bc9,0xbd7bbc48,0xbd62bcf1,0x80003d80,0xbc953d75,0xbd0e3d55,0xbd463d22,0x3cc4bd6d,0x3d22bd46,0x3d55bd0e,0x3d75bc95,0xbd35bd35,0xbcf1bd62,0xbc48bd7b,0x3bc9bd7f,
0x3d353d35,0x3c953d75,0xbc483d7b,0xbd223d46,0xbd6d3cc4,0xbd7fbbc9,0xbd55bd0e,0xbcf1bd62,0xbd800000,0xbd62bcf1,0xbd0ebd55,0xbbc9bd7f,0x3cc4bd6d,0x3d46bd22,0x3d7bbc48,0x3d753c95,
0xbd353d35,0xbd753c95,0xbd7bbc48,0xbd46bd22,0xbcc4bd6d,0x3bc9bd7f,0x3d0ebd55,0x3d62bcf1,0x8000bd80,0x3cf1bd62,0x3d55bd0e,0x3d7fbbc9,0x3d6d3cc4,0x3d223d46,0x3c483d7b,0xbc953d75,
0x3cc4bd6d,0x3d62bcf1,0x3d7b3c48,0x3d223d46,0xbd353d35,0xbd7f3bc9,0xbd55bd0e,0xbc95bd75,0x3d6dbcc4,0x3d753c95,0x3d0e3d55,0xbbc93d7f,0xbd800000,0xbd46bd22,0xbc48bd7b,0x3cf1bd62,
0xbd6dbcc4,0xbcf1bd62,0x3c48bd7b,0x3d46bd22,0x3d353d35,0x3bc93d7f,0xbd0e3d55,0xbd753c95,0xbcc4bd6d,0x3c95bd75,0x3d55bd0e,0x3d7f3bc9,0x80003d80,0xbd223d46,0xbd7b3c48,0xbd62bcf1,
0x8000bd80,0x3d46bd22,0x3d7b3c48,0x3cf13d62,0xbcc43d6d,0xbd753c95,0xbd55bd0e,0xbbc9bd7f,0x3d35bd35,0x3d7f3bc9,0x3d0e3d55,0xbc953d75,0xbd6d3cc4,0xbd62bcf1,0xbc48bd7b,0x3d22bd46,
0xbd800000,0xbd22bd46,0x3c48bd7b,0x3d62bcf1,0x3d6d3cc4,0x3c953d75,0xbd0e3d55,0xbd7f3bc9,0xbd35bd35,0x3bc9bd7f,0x3d55bd0e,0x3d753c95,0x3cc43d6d,0xbcf13d62,0xbd7b3c48,0xbd46bd22,
0x3d6dbcc4,0x3d463d22,0xbc483d7b,0xbd753c95,0x80003d80,0xbd623cf1,0xbd55bd0e,0x3bc9bd7f,0xbcc43d6d,0xbd7f3bc9,0xbd0ebd55,0x3cf1bd62,0xbd35bd35,0x3c95bd75,0x3d7bbc48,0x3d223d46,
0x3cc43d6d,0xbd223d46,0xbd7bbc48,0xbc95bd75,0xbd800000,0xbcf1bd62,0x3d0ebd55,0x3d7f3bc9,0xbd6dbcc4,0xbbc9bd7f,0x3d55bd0e,0x3d623cf1,0x3d35bd35,0x3d753c95,0x3c483d7b,0xbd463d22,
0xbd353d35,0xbd62bcf1,0x3c48bd7b,0x3d7fbbc9,0x3cc43d6d,0xbd463d22,0xbd55bd0e,0x3c95bd75,0x8000bd80,0x3d75bc95,0x3d0e3d55,0xbd223d46,0xbd6dbcc4,0x3bc9bd7f,0x3d7bbc48,0x3cf13d62,
0x3d353d35,0xbcf13d62,0xbd7bbc48,0xbbc9bd7f,0x3d6dbcc4,0x3d223d46,0xbd0e3d55,0xbd75bc95,0xbd800000,0xbc95bd75,0x3d55bd0e,0x3d463d22,0xbcc43d6d,0xbd7fbbc9,0xbc48bd7b,0x3d62bcf1,
0x3d6d3cc4,0xbc953d75,0xbd7bbc48,0x3bc9bd7f,0x3d353d35,0xbd223d46,0xbd55bd0e,0x3cf1bd62,0x3cc43d6d,0xbd623cf1,0xbd0ebd55,0x3d46bd22,0x80003d80,0xbd7f3bc9,0xbc48bd7b,0x3d75bc95,
0xbcc43d6d,0xbd75bc95,0x3c48bd7b,0x3d7f3bc9,0xbd353d35,0xbd46bd22,0x3d0ebd55,0x3d623cf1,0xbd6d3cc4,0xbcf1bd62,0x3d55bd0e,0x3d223d46,0xbd800000,0xbbc9bd7f,0x3d7bbc48,0x3c953d75,
0x3d80,0xbd7fbbc9,0x3c48bd7b,0x3d753c95,0xbcc43d6d,0xbd62bcf1,0x3d0ebd55,0x3d463d22,0xbd353d35,0xbd22bd46,0x3d55bd0e,0x3cf13d62,0xbd6d3cc4,0xbc95bd75,0x3d7bbc48,0x3bc93d7f,
0xbd800000,0x3bc9bd7f,0x3d7b3c48,0xbc953d75,0xbd6dbcc4,0x3cf1bd62,0x3d553d0e,0xbd223d46,0xbd35bd35,0x3d46bd22,0x3d0e3d55,0xbd623cf1,0xbcc4bd6d,0x3d75bc95,0x3c483d7b,0xbd7f3bc9,
0xbd6d3cc4,0xbbc9bd7f,0x3d7b3c48,0xbcf13d62,0x3d80,0xbd75bc95,0x3d0ebd55,0x3d223d46,0x3cc4bd6d,0x3d463d22,0xbd553d0e,0xbc95bd75,0xbd35bd35,0x3d62bcf1,0x3c483d7b,0xbd7fbbc9,
0x3cc43d6d,0xbd7f3bc9,0x3c48bd7b,0x3d623cf1,0x3d800000,0xbc953d75,0xbd55bd0e,0x3d46bd22,0xbd6dbcc4,0x3d22bd46,0x3d0e3d55,0xbd753c95,0xbd353d35,0xbcf1bd62,0x3d7bbc48,0xbbc93d7f,
0x3d35bd35,0x3c953d75,0xbd7bbc48,0x3d22bd46,0x3cc43d6d,0xbd7fbbc9,0x3d0ebd55,0x3cf13d62,0x3d80,0xbd62bcf1,0x3d55bd0e,0x3bc93d7f,0xbd6dbcc4,0x3d46bd22,0x3c483d7b,0xbd75bc95,
0x3d353d35,0xbd753c95,0x3c48bd7b,0x3d463d22,0xbd6d3cc4,0x3bc9bd7f,0x3d553d0e,0xbd623cf1,0xbd800000,0x3cf1bd62,0x3d0e3d55,0xbd7f3bc9,0x3cc4bd6d,0x3d223d46,0xbd7b3c48,0x3c95bd75,
0xbd6dbcc4,0x3d62bcf1,0xbc483d7b,0xbd22bd46,0x3d353d35,0xbd7f3bc9,0x3d0ebd55,0x3c953d75,0xbcc4bd6d,0x3d753c95,0xbd553d0e,0x3bc9bd7f,0x3d80,0xbd46bd22,0x3d7bbc48,0xbcf13d62,
0xbcc43d6d,0xbcf1bd62,0x3d7b3c48,0xbd463d22,0x3d35bd35,0x3bc93d7f,0xbd55bd0e,0x3d75bc95,0xbd6d3cc4,0x3c95bd75,0x3d0e3d55,0xbd7fbbc9,0x3d800000,0xbd223d46,0xbc48bd7b,0x3d623cf1,
0xbd800000,0x3d46bd22,0xbc483d7b,0xbcf1bd62,0x3d6d3cc4,0xbd753c95,0x3d0ebd55,0x3bc93d7f,0xbd35bd35,0x3d7f3bc9,0xbd553d0e,0x3c95bd75,0x3cc43d6d,0xbd62bcf1,0x3d7bbc48,0xbd223d46,
0x3d80,0xbd22bd46,0x3d7b3c48,0xbd623cf1,0x3cc4bd6d,0x3c953d75,0xbd55bd0e,0x3d7fbbc9,0xbd353d35,0x3bc9bd7f,0x3d0e3d55,0xbd75bc95,0x3d6dbcc4,0xbcf13d62,0xbc48bd7b,0x3d463d22,
0xbcc4bd6d,0x3d463d22,0xbd7bbc48,0x3d75bc95,0x3d800000,0xbd623cf1,0x3d0ebd55,0xbbc93d7f,0x3d6d3cc4,0xbd7f3bc9,0x3d55bd0e,0xbcf13d62,0xbd353d35,0x3c95bd75,0x3c483d7b,0xbd22bd46,
0x3d6dbcc4,0xbd223d46,0x3c48bd7b,0x3c953d75,0x3d80,0xbcf1bd62,0x3d553d0e,0xbd7fbbc9,0xbcc43d6d,0xbbc9bd7f,0x3d0e3d55,0xbd62bcf1,0xbd35bd35,0x3d753c95,0xbd7b3c48,0x3d46bd22,
0x3d353d35,0xbd62bcf1,0x3d7b3c48,0xbd7f3bc9,0x3d6dbcc4,0xbd463d22,0x3d0ebd55,0xbc953d75,0xbd800000,0x3d75bc95,0xbd553d0e,0x3d22bd46,0xbcc43d6d,0x3bc9bd7f,0x3c483d7b,0xbcf1bd62,
0x3d35bd35,0xbcf13d62,0x3c48bd7b,0x3bc93d7f,0xbcc4bd6d,0x3d223d46,0xbd55bd0e,0x3d753c95,0x3d80,0xbc95bd75,0x3d0e3d55,0xbd46bd22,0x3d6d3cc4,0xbd7fbbc9,0x3d7bbc48,0xbd623cf1,
0x3cc4bd6d,0xbc953d75,0x3c48bd7b,0xbbc93d7f,0x3d35bd35,0xbd223d46,0x3d0ebd55,0xbcf13d62,0x3d6dbcc4,0xbd623cf1,0x3d55bd0e,0xbd463d22,0x3d800000,0xbd7f3bc9,0x3d7bbc48,0xbd753c95,
0x3d6d3cc4,0xbd75bc95,0x3d7b3c48,0xbd7fbbc9,0x3d353d35,0xbd46bd22,0x3d553d0e,0xbd62bcf1,0x3cc43d6d,0xbcf1bd62,0x3d0e3d55,0xbd22bd46,0x3d80,0xbbc9bd7f,0x3c483d7b,0xbc95bd75,
0xbd800000,0x3bc9bd7f,0x3d7b3c48,0xbc953d75,0xbd6dbcc4,0x3cf1bd62,0x3d553d0e,0xbd223d46,0xbd35bd35,0x3d46bd22,0x3d0e3d55,0xbd623cf1,0xbcc4bd6d,0x3d75bc95,0x3c483d7b,0xbd7f3bc9,
0x8000bd80,0x3d7f3bc9,0xbc483d7b,0xbd75bc95,0x3cc4bd6d,0x3d623cf1,0xbd0e3d55,0xbd46bd22,0x3d35bd35,0x3d223d46,0xbd553d0e,0xbcf1bd62,0x3d6dbcc4,0x3c953d75,0xbd7b3c48,0xbbc9bd7f,
0xbcc4bd6d,0x3d7fbbc9,0xbc483d7b,0xbd62bcf1,0xbd800000,0x3c95bd75,0x3d553d0e,0xbd463d22,0x3d6d3cc4,0xbd223d46,0xbd0ebd55,0x3d75bc95,0x3d35bd35,0x3cf13d62,0xbd7b3c48,0x3bc9bd7f,
0xbd6d3cc4,0xbbc9bd7f,0x3d7b3c48,0xbcf13d62,0x80003d80,0xbd75bc95,0x3d0ebd55,0x3d223d46,0x3cc4bd6d,0x3d463d22,0xbd553d0e,0xbc95bd75,0xbd35bd35,0x3d62bcf1,0x3c483d7b,0xbd7fbbc9,
0x3d353d35,0xbd753c95,0x3c48bd7b,0x3d463d22,0xbd6d3cc4,0x3bc9bd7f,0x3d553d0e,0xbd623cf1,0xbd800000,0x3cf1bd62,0x3d0e3d55,0xbd7f3bc9,0x3cc4bd6d,0x3d223d46,0xbd7b3c48,0x3c95bd75,
0xbd353d35,0xbc95bd75,0x3d7b3c48,0xbd223d46,0xbcc4bd6d,0x3d7f3bc9,0xbd0e3d55,0xbcf1bd62,0x8000bd80,0x3d623cf1,0xbd553d0e,0xbbc9bd7f,0x3d6d3cc4,0xbd463d22,0xbc48bd7b,0x3d753c95,
0x3cc4bd6d,0x3cf13d62,0xbd7bbc48,0x3d46bd22,0xbd353d35,0xbbc9bd7f,0x3d553d0e,0xbd753c95,0x3d6dbcc4,0xbc953d75,0xbd0ebd55,0x3d7f3bc9,0xbd800000,0x3d22bd46,0x3c483d7b,0xbd62bcf1,
0xbd6dbcc4,0x3d62bcf1,0xbc483d7b,0xbd22bd46,0x3d353d35,0xbd7f3bc9,0x3d0ebd55,0x3c953d75,0xbcc4bd6d,0x3d753c95,0xbd553d0e,0x3bc9bd7f,0x80003d80,0xbd46bd22,0x3d7bbc48,0xbcf13d62,
0x8000bd80,0x3d223d46,0xbd7bbc48,0x3d62bcf1,0xbcc43d6d,0xbc95bd75,0x3d553d0e,0xbd7f3bc9,0x3d35bd35,0xbbc93d7f,0xbd0ebd55,0x3d753c95,0xbd6d3cc4,0x3cf1bd62,0x3c483d7b,0xbd46bd22,
0xbd800000,0x3d46bd22,0xbc483d7b,0xbcf1bd62,0x3d6d3cc4,0xbd753c95,0x3d0ebd55,0x3bc93d7f,0xbd35bd35,0x3d7f3bc9,0xbd553d0e,0x3c95bd75,0x3cc43d6d,0xbd62bcf1,0x3d7bbc48,0xbd223d46,
0x3d6dbcc4,0xbd223d46,0x3c48bd7b,0x3c953d75,0x80003d80,0xbcf1bd62,0x3d553d0e,0xbd7fbbc9,0xbcc43d6d,0xbbc9bd7f,0x3d0e3d55,0xbd62bcf1,0xbd35bd35,0x3d753c95,0xbd7b3c48,0x3d46bd22,
0x3cc43d6d,0xbd46bd22,0x3d7b3c48,0xbd753c95,0xbd800000,0x3d62bcf1,0xbd0e3d55,0x3bc9bd7f,0xbd6dbcc4,0x3d7fbbc9,0xbd553d0e,0x3cf1bd62,0x3d35bd35,0xbc953d75,0xbc48bd7b,0x3d223d46,
0xbd353d35,0x3cf1bd62,0xbc483d7b,0xbbc9bd7f,0x3cc43d6d,0xbd22bd46,0x3d553d0e,0xbd75bc95,0x8000bd80,0x3c953d75,0xbd0ebd55,0x3d463d22,0xbd6dbcc4,0x3d7f3bc9,0xbd7b3c48,0x3d62bcf1,
0x3d353d35,0xbd62bcf1,0x3d7b3c48,0xbd7f3bc9,0x3d6dbcc4,0xbd463d22,0x3d0ebd55,0xbc953d75,0xbd800000,0x3d75bc95,0xbd553d0e,0x3d22bd46,0xbcc43d6d,0x3bc9bd7f,0x3c483d7b,0xbcf1bd62,
0x3d6d3cc4,0xbd75bc95,0x3d7b3c48,0xbd7fbbc9,0x3d353d35,0xbd46bd22,0x3d553d0e,0xbd62bcf1,0x3cc43d6d,0xbcf1bd62,0x3d0e3d55,0xbd22bd46,0x80003d80,0xbbc9bd7f,0x3c483d7b,0xbc95bd75,
0xbcc43d6d,0x3c95bd75,0xbc483d7b,0x3bc9bd7f,0xbd353d35,0x3d22bd46,0xbd0e3d55,0x3cf1bd62,0xbd6d3cc4,0x3d62bcf1,0xbd553d0e,0x3d46bd22,0xbd800000,0x3d7fbbc9,0xbd7b3c48,0x3d75bc95,
0x3d80,0x3bc9bd7f,0xbc483d7b,0x3c95bd75,0xbcc43d6d,0x3cf1bd62,0xbd0e3d55,0x3d22bd46,0xbd353d35,0x3d46bd22,0xbd553d0e,0x3d62bcf1,0xbd6d3cc4,0x3d75bc95,0xbd7b3c48,0x3d7fbbc9,
0xbd800000,0x3d7f3bc9,0xbd7bbc48,0x3d753c95,0xbd6dbcc4,0x3d623cf1,0xbd55bd0e,0x3d463d22,0xbd35bd35,0x3d223d46,0xbd0ebd55,0x3cf13d62,0xbcc4bd6d,0x3c953d75,0xbc48bd7b,0x3bc93d7f,
0xbd6d3cc4,0x3d7fbbc9,0xbd7bbc48,0x3d623cf1,0x3d80,0x3c95bd75,0xbd0e3d55,0x3d46bd22,0x3cc4bd6d,0xbd223d46,0x3d55bd0e,0xbd753c95,0xbd35bd35,0x3cf13d62,0xbc48bd7b,0xbbc93d7f,
0x3cc43d6d,0xbbc9bd7f,0xbc483d7b,0x3cf1bd62,0x3d800000,0xbd75bc95,0x3d553d0e,0xbd22bd46,0xbd6dbcc4,0x3d463d22,0xbd0ebd55,0x3c953d75,0xbd353d35,0x3d62bcf1,0xbd7b3c48,0x3d7f3bc9,
0x3d35bd35,0xbd753c95,0x3d7b3c48,0xbd46bd22,0x3cc43d6d,0x3bc9bd7f,0xbd0e3d55,0x3d62bcf1,0x3d80,0x3cf1bd62,0xbd553d0e,0x3d7fbbc9,0xbd6dbcc4,0x3d223d46,0xbc48bd7b,0xbc953d75,
0x3d353d35,0xbc95bd75,0xbc483d7b,0x3d22bd46,0xbd6d3cc4,0x3d7f3bc9,0xbd55bd0e,0x3cf13d62,0xbd800000,0x3d623cf1,0xbd0ebd55,0x3bc93d7f,0x3cc4bd6d,0xbd463d22,0x3d7bbc48,0xbd75bc95,
0xbd6dbcc4,0x3cf13d62,0x3c48bd7b,0xbd463d22,0x3d353d35,0xbbc9bd7f,0xbd0e3d55,0x3d75bc95,0xbcc4bd6d,0xbc953d75,0x3d55bd0e,0xbd7fbbc9,0x3d80,0x3d22bd46,0xbd7b3c48,0x3d623cf1,
0xbcc43d6d,0x3d62bcf1,0xbd7bbc48,0x3d223d46,0x3d35bd35,0xbd7f3bc9,0x3d553d0e,0xbc95bd75,0xbd6d3cc4,0x3d753c95,0xbd0ebd55,0xbbc93d7f,0x3d800000,0xbd46bd22,0x3c483d7b,0x3cf1bd62,
0xbd800000,0x3d223d46,0x3c48bd7b,0xbd623cf1,0x3d6d3cc4,0xbc95bd75,0xbd0e3d55,0x3d7fbbc9,0xbd35bd35,0xbbc93d7f,0x3d55bd0e,0xbd75bc95,0x3cc43d6d,0x3cf1bd62,0xbd7b3c48,0x3d463d22,
0x3d80,0x3d46bd22,0xbd7bbc48,0x3cf13d62,0x3cc4bd6d,0xbd753c95,0x3d553d0e,0xbbc9bd7f,0xbd353d35,0x3d7f3bc9,0xbd0ebd55,0xbc953d75,0x3d6dbcc4,0xbd62bcf1,0x3c483d7b,0x3d22bd46,
0xbcc4bd6d,0xbd223d46,0x3d7b3c48,0xbc95bd75,0x3d800000,0xbcf1bd62,0xbd0e3d55,0x3d7f3bc9,0x3d6d3cc4,0xbbc9bd7f,0xbd553d0e,0x3d623cf1,0xbd353d35,0x3d753c95,0xbc48bd7b,0xbd463d22,
0x3d6dbcc4,0xbd46bd22,0xbc483d7b,0x3d75bc95,0x3d80,0x3d62bcf1,0xbd55bd0e,0xbbc93d7f,0xbcc43d6d,0x3d7fbbc9,0xbd0ebd55,0xbcf13d62,0xbd35bd35,0xbc953d75,0x3d7bbc48,0xbd22bd46,
0x3d353d35,0x3cf1bd62,0xbd7bbc48,0x3bc93d7f,0x3d6dbcc4,0xbd22bd46,0xbd0e3d55,0x3d753c95,0xbd800000,0x3c953d75,0x3d55bd0e,0xbd46bd22,0xbcc43d6d,0x3d7f3bc9,0xbc48bd7b,0xbd623cf1,
0x3d35bd35,0xbd62bcf1,0xbc483d7b,0x3d7fbbc9,0xbcc4bd6d,0xbd463d22,0x3d553d0e,0x3c95bd75,0x3d80,0x3d75bc95,0xbd0ebd55,0xbd223d46,0x3d6d3cc4,0x3bc9bd7f,0xbd7b3c48,0x3cf13d62,
0x3cc4bd6d,0xbd75bc95,0xbc483d7b,0x3d7f3bc9,0x3d35bd35,0xbd46bd22,0xbd0e3d55,0x3d623cf1,0x3d6dbcc4,0xbcf1bd62,0xbd553d0e,0x3d223d46,0x3d800000,0xbbc9bd7f,0xbd7b3c48,0x3c953d75,
0x3d6d3cc4,0x3c95bd75,0xbd7bbc48,0xbbc93d7f,0x3d353d35,0x3d22bd46,0xbd55bd0e,0xbcf13d62,0x3cc43d6d,0x3d62bcf1,0xbd0ebd55,0xbd463d22,0x3d80,0x3d7fbbc9,0xbc48bd7b,0xbd753c95,
0xbd800000,0x3d7f3bc9,0xbd7bbc48,0x3d753c95,0xbd6dbcc4,0x3d623cf1,0xbd55bd0e,0x3d463d22,0xbd35bd35,0x3d223d46,0xbd0ebd55,0x3cf13d62,0xbcc4bd6d,0x3c953d75,0xbc48bd7b,0x3bc93d7f,
0x8000bd80,0xbbc93d7f,0x3c48bd7b,0xbc953d75,0x3cc4bd6d,0xbcf13d62,0x3d0ebd55,0xbd223d46,0x3d35bd35,0xbd463d22,0x3d55bd0e,0xbd623cf1,0x3d6dbcc4,0xbd753c95,0x3d7bbc48,0xbd7f3bc9,
0xbcc4bd6d,0x3bc93d7f,0x3c48bd7b,0xbcf13d62,0xbd800000,0x3d753c95,0xbd55bd0e,0x3d223d46,0x3d6d3cc4,0xbd46bd22,0x3d0e3d55,0xbc95bd75,0x3d35bd35,0xbd623cf1,0x3d7bbc48,0xbd7fbbc9,
0xbd6d3cc4,0x3d7fbbc9,0xbd7bbc48,0x3d623cf1,0x80003d80,0x3c95bd75,0xbd0e3d55,0x3d46bd22,0x3cc4bd6d,0xbd223d46,0x3d55bd0e,0xbd753c95,0xbd35bd35,0x3cf13d62,0xbc48bd7b,0xbbc93d7f,
0x3d353d35,0xbc95bd75,0xbc483d7b,0x3d22bd46,0xbd6d3cc4,0x3d7f3bc9,0xbd55bd0e,0x3cf13d62,0xbd800000,0x3d623cf1,0xbd0ebd55,0x3bc93d7f,0x3cc4bd6d,0xbd463d22,0x3d7bbc48,0xbd75bc95,
0xbd353d35,0x3d75bc95,0xbd7bbc48,0x3d463d22,0xbcc4bd6d,0xbbc93d7f,0x3d0ebd55,0xbd623cf1,0x8000bd80,0xbcf13d62,0x3d55bd0e,0xbd7f3bc9,0x3d6d3cc4,0xbd22bd46,0x3c483d7b,0x3c95bd75,
0x3cc4bd6d,0xbd623cf1,0x3d7b3c48,0xbd22bd46,0xbd353d35,0x3d7fbbc9,0xbd55bd0e,0x3c953d75,0x3d6dbcc4,0xbd75bc95,0x3d0e3d55,0x3bc9bd7f,0xbd800000,0x3d463d22,0xbc48bd7b,0xbcf13d62,
0xbd6dbcc4,0x3cf13d62,0x3c48bd7b,0xbd463d22,0x3d353d35,0xbbc9bd7f,0xbd0e3d55,0x3d75bc95,0xbcc4bd6d,0xbc953d75,0x3d55bd0e,0xbd7fbbc9,0x80003d80,0x3d22bd46,0xbd7b3c48,0x3d623cf1,
0x8000bd80,0xbd463d22,0x3d7b3c48,0xbcf1bd62,0xbcc43d6d,0x3d75bc95,0xbd55bd0e,0x3bc93d7f,0x3d35bd35,0xbd7fbbc9,0x3d0e3d55,0x3c95bd75,0xbd6d3cc4,0x3d623cf1,0xbc48bd7b,0xbd223d46,
0xbd800000,0x3d223d46,0x3c48bd7b,0xbd623cf1,0x3d6d3cc4,0xbc95bd75,0xbd0e3d55,0x3d7fbbc9,0xbd35bd35,0xbbc93d7f,0x3d55bd0e,0xbd75bc95,0x3cc43d6d,0x3cf1bd62,0xbd7b3c48,0x3d463d22,
0x3d6dbcc4,0xbd46bd22,0xbc483d7b,0x3d75bc95,0x80003d80,0x3d62bcf1,0xbd55bd0e,0xbbc93d7f,0xbcc43d6d,0x3d7fbbc9,0xbd0ebd55,0xbcf13d62,0xbd35bd35,0xbc953d75,0x3d7bbc48,0xbd22bd46,
0x3cc43d6d,0x3d22bd46,0xbd7bbc48,0x3c953d75,0xbd800000,0x3cf13d62,0x3d0ebd55,0xbd7fbbc9,0xbd6dbcc4,0x3bc93d7f,0x3d55bd0e,0xbd62bcf1,0x3d35bd35,0xbd75bc95,0x3c483d7b,0x3d46bd22,
0xbd353d35,0x3d623cf1,0x3c48bd7b,0xbd7f3bc9,0x3cc43d6d,0x3d46bd22,0xbd55bd0e,0xbc953d75,0x8000bd80,0xbd753c95,0x3d0e3d55,0x3d22bd46,0xbd6dbcc4,0xbbc93d7f,0x3d7bbc48,0xbcf1bd62,
0x3d353d35,0x3cf1bd62,0xbd7bbc48,0x3bc93d7f,0x3d6dbcc4,0xbd22bd46,0xbd0e3d55,0x3d753c95,0xbd800000,0x3c953d75,0x3d55bd0e,0xbd46bd22,0xbcc43d6d,0x3d7f3bc9,0xbc48bd7b,0xbd623cf1,
0x3d6d3cc4,0x3c95bd75,0xbd7bbc48,0xbbc93d7f,0x3d353d35,0x3d22bd46,0xbd55bd0e,0xbcf13d62,0x3cc43d6d,0x3d62bcf1,0xbd0ebd55,0xbd463d22,0x80003d80,0x3d7fbbc9,0xbc48bd7b,0xbd753c95,
0xbcc43d6d,0x3d753c95,0x3c48bd7b,0xbd7fbbc9,0xbd353d35,0x3d463d22,0x3d0ebd55,0xbd62bcf1,0xbd6d3cc4,0x3cf13d62,0x3d55bd0e,0xbd22bd46,0xbd800000,0x3bc93d7f,0x3d7bbc48,0xbc95bd75,
0x3d80,0x3d7f3bc9,0x3c48bd7b,0xbd75bc95,0xbcc43d6d,0x3d623cf1,0x3d0ebd55,0xbd46bd22,0xbd353d35,0x3d223d46,0x3d55bd0e,0xbcf1bd62,0xbd6d3cc4,0x3c953d75,0x3d7bbc48,0xbbc9bd7f,
0xbd800000,0xbbc93d7f,0x3d7b3c48,0x3c95bd75,0xbd6dbcc4,0xbcf13d62,0x3d553d0e,0x3d22bd46,0xbd35bd35,0xbd463d22,0x3d0e3d55,0x3d62bcf1,0xbcc4bd6d,0xbd753c95,0x3c483d7b,0x3d7fbbc9,
0xbd6d3cc4,0x3bc93d7f,0x3d7b3c48,0x3cf1bd62,0x3d80,0x3d753c95,0x3d0ebd55,0xbd22bd46,0x3cc4bd6d,0xbd46bd22,0xbd553d0e,0x3c953d75,0xbd35bd35,0xbd623cf1,0x3c483d7b,0x3d7f3bc9,
0x3cc43d6d,0x3d7fbbc9,0x3c48bd7b,0xbd62bcf1,0x3d800000,0x3c95bd75,0xbd55bd0e,0xbd463d22,0xbd6dbcc4,0xbd223d46,0x3d0e3d55,0x3d75bc95,0xbd353d35,0x3cf13d62,0x3d7bbc48,0x3bc9bd7f,
0x3d35bd35,0xbc95bd75,0xbd7bbc48,0xbd223d46,0x3cc43d6d,0x3d7f3bc9,0x3d0ebd55,0xbcf1bd62,0x3d80,0x3d623cf1,0x3d55bd0e,0xbbc9bd7f,0xbd6dbcc4,0xbd463d22,0x3c483d7b,0x3d753c95,
0x3d353d35,0x3d75bc95,0x3c48bd7b,0xbd46bd22,0xbd6d3cc4,0xbbc93d7f,0x3d553d0e,0x3d62bcf1,0xbd800000,0xbcf13d62,0x3d0e3d55,0x3d7fbbc9,0x3cc4bd6d,0xbd22bd46,0xbd7b3c48,0xbc953d75,
0xbd6dbcc4,0xbd623cf1,0xbc483d7b,0x3d223d46,0x3d353d35,0x3d7fbbc9,0x3d0ebd55,0xbc95bd75,0xbcc4bd6d,0xbd75bc95,0xbd553d0e,0xbbc93d7f,0x3d80,0x3d463d22,0x3d7bbc48,0x3cf1bd62,
0xbcc43d6d,0x3cf13d62,0x3d7b3c48,0x3d46bd22,0x3d35bd35,0xbbc9bd7f,0xbd55bd0e,0xbd753c95,0xbd6d3cc4,0xbc953d75,0x3d0e3d55,0x3d7f3bc9,0x3d800000,0x3d22bd46,0xbc48bd7b,0xbd62bcf1,
0xbd800000,0xbd463d22,0xbc483d7b,0x3cf13d62,0x3d6d3cc4,0x3d75bc95,0x3d0ebd55,0xbbc9bd7f,0xbd35bd35,0xbd7fbbc9,0xbd553d0e,0xbc953d75,0x3cc43d6d,0x3d623cf1,0x3d7bbc48,0x3d22bd46,
0x3d80,0x3d223d46,0x3d7b3c48,0x3d62bcf1,0x3cc4bd6d,0xbc95bd75,0xbd55bd0e,0xbd7f3bc9,0xbd353d35,0xbbc93d7f,0x3d0e3d55,0x3d753c95,0x3d6dbcc4,0x3cf1bd62,0xbc48bd7b,0xbd46bd22,
0xbcc4bd6d,0xbd46bd22,0xbd7bbc48,0xbd753c95,0x3d800000,0x3d62bcf1,0x3d0ebd55,0x3bc9bd7f,0x3d6d3cc4,0x3d7fbbc9,0x3d55bd0e,0x3cf1bd62,0xbd353d35,0xbc953d75,0x3c483d7b,0x3d223d46,
0x3d6dbcc4,0x3d22bd46,0x3c48bd7b,0xbc95bd75,0x3d80,0x3cf13d62,0x3d553d0e,0x3d7f3bc9,0xbcc43d6d,0x3bc93d7f,0x3d0e3d55,0x3d623cf1,0xbd35bd35,0xbd75bc95,0xbd7b3c48,0xbd463d22,
0x3d353d35,0x3d623cf1,0x3d7b3c48,0x3d7fbbc9,0x3d6dbcc4,0x3d46bd22,0x3d0ebd55,0x3c95bd75,0xbd800000,0xbd753c95,0xbd553d0e,0xbd223d46,0xbcc43d6d,0xbbc93d7f,0x3c483d7b,0x3cf13d62,
0x3d35bd35,0x3cf1bd62,0x3c48bd7b,0xbbc9bd7f,0xbcc4bd6d,0xbd22bd46,0xbd55bd0e,0xbd75bc95,0x3d80,0x3c953d75,0x3d0e3d55,0x3d463d22,0x3d6d3cc4,0x3d7f3bc9,0x3d7bbc48,0x3d62bcf1,
0x3cc4bd6d,0x3c95bd75,0x3c48bd7b,0x3bc9bd7f,0x3d35bd35,0x3d22bd46,0x3d0ebd55,0x3cf1bd62,0x3d6dbcc4,0x3d62bcf1,0x3d55bd0e,0x3d46bd22,0x3d800000,0x3d7fbbc9,0x3d7bbc48,0x3d75bc95,
0x3d6d3cc4,0x3d753c95,0x3d7b3c48,0x3d7f3bc9,0x3d353d35,0x3d463d22,0x3d553d0e,0x3d623cf1,0x3cc43d6d,0x3cf13d62,0x3d0e3d55,0x3d223d46,0x3d80,0x3bc93d7f,0x3c483d7b,0x3c953d75,
0xbd800000,0xbbc93d7f,0x3d7b3c48,0x3c95bd75,0xbd6dbcc4,0xbcf13d62,0x3d553d0e,0x3d22bd46,0xbd35bd35,0xbd463d22,0x3d0e3d55,0x3d62bcf1,0xbcc4bd6d,0xbd753c95,0x3c483d7b,0x3d7fbbc9,
0x8000bd80,0xbd7fbbc9,0xbc483d7b,0x3d753c95,0x3cc4bd6d,0xbd62bcf1,0xbd0e3d55,0x3d463d22,0x3d35bd35,0xbd22bd46,0xbd553d0e,0x3cf13d62,0x3d6dbcc4,0xbc95bd75,0xbd7b3c48,0x3bc93d7f,
0xbcc4bd6d,0xbd7f3bc9,0xbc483d7b,0x3d623cf1,0xbd800000,0xbc953d75,0x3d553d0e,0x3d46bd22,0x3d6d3cc4,0x3d22bd46,0xbd0ebd55,0xbd753c95,0x3d35bd35,0xbcf1bd62,0xbd7b3c48,0xbbc93d7f,
0xbd6d3cc4,0x3bc93d7f,0x3d7b3c48,0x3cf1bd62,0x80003d80,0x3d753c95,0x3d0ebd55,0xbd22bd46,0x3cc4bd6d,0xbd46bd22,0xbd553d0e,0x3c953d75,0xbd35bd35,0xbd623cf1,0x3c483d7b,0x3d7f3bc9,
0x3d353d35,0x3d75bc95,0x3c48bd7b,0xbd46bd22,0xbd6d3cc4,0xbbc93d7f,0x3d553d0e,0x3d62bcf1,0xbd800000,0xbcf13d62,0x3d0e3d55,0x3d7fbbc9,0x3cc4bd6d,0xbd22bd46,0xbd7b3c48,0xbc953d75,
0xbd353d35,0x3c953d75,0x3d7b3c48,0x3d22bd46,0xbcc4bd6d,0xbd7fbbc9,0xbd0e3d55,0x3cf13d62,0x8000bd80,0xbd62bcf1,0xbd553d0e,0x3bc93d7f,0x3d6d3cc4,0x3d46bd22,0xbc48bd7b,0xbd75bc95,
0x3cc4bd6d,0xbcf1bd62,0xbd7bbc48,0xbd463d22,0xbd353d35,0x3bc93d7f,0x3d553d0e,0x3d75bc95,0x3d6dbcc4,0x3c95bd75,0xbd0ebd55,0xbd7fbbc9,0xbd800000,0xbd223d46,0x3c483d7b,0x3d623cf1,
0xbd6dbcc4,0xbd623cf1,0xbc483d7b,0x3d223d46,0x3d353d35,0x3d7fbbc9,0x3d0ebd55,0xbc95bd75,0xbcc4bd6d,0xbd75bc95,0xbd553d0e,0xbbc93d7f,0x80003d80,0x3d463d22,0x3d7bbc48,0x3cf1bd62,
0x8000bd80,0xbd22bd46,0xbd7bbc48,0xbd623cf1,0xbcc43d6d,0x3c953d75,0x3d553d0e,0x3d7fbbc9,0x3d35bd35,0x3bc9bd7f,0xbd0ebd55,0xbd75bc95,0xbd6d3cc4,0xbcf13d62,0x3c483d7b,0x3d463d22,
0xbd800000,0xbd463d22,0xbc483d7b,0x3cf13d62,0x3d6d3cc4,0x3d75bc95,0x3d0ebd55,0xbbc9bd7f,0xbd35bd35,0xbd7fbbc9,0xbd553d0e,0xbc953d75,0x3cc43d6d,0x3d623cf1,0x3d7bbc48,0x3d22bd46,
0x3d6dbcc4,0x3d22bd46,0x3c48bd7b,0xbc95bd75,0x80003d80,0x3cf13d62,0x3d553d0e,0x3d7f3bc9,0xbcc43d6d,0x3bc93d7f,0x3d0e3d55,0x3d623cf1,0xbd35bd35,0xbd75bc95,0xbd7b3c48,0xbd463d22,
0x3cc43d6d,0x3d463d22,0x3d7b3c48,0x3d75bc95,0xbd800000,0xbd623cf1,0xbd0e3d55,0xbbc93d7f,0xbd6dbcc4,0xbd7f3bc9,0xbd553d0e,0xbcf13d62,0x3d35bd35,0x3c95bd75,0xbc48bd7b,0xbd22bd46,
0xbd353d35,0xbcf13d62,0xbc483d7b,0x3bc93d7f,0x3cc43d6d,0x3d223d46,0x3d553d0e,0x3d753c95,0x8000bd80,0xbc95bd75,0xbd0ebd55,0xbd46bd22,0xbd6dbcc4,0xbd7fbbc9,0xbd7b3c48,0xbd623cf1,
0x3d353d35,0x3d623cf1,0x3d7b3c48,0x3d7fbbc9,0x3d6dbcc4,0x3d46bd22,0x3d0ebd55,0x3c95bd75,0xbd800000,0xbd753c95,0xbd553d0e,0xbd223d46,0xbcc43d6d,0xbbc93d7f,0x3c483d7b,0x3cf13d62,
0x3d6d3cc4,0x3d753c95,0x3d7b3c48,0x3d7f3bc9,0x3d353d35,0x3d463d22,0x3d553d0e,0x3d623cf1,0x3cc43d6d,0x3cf13d62,0x3d0e3d55,0x3d223d46,0x80003d80,0x3bc93d7f,0x3c483d7b,0x3c953d75,
0xbcc43d6d,0xbc953d75,0xbc483d7b,0xbbc93d7f,0xbd353d35,0xbd223d46,0xbd0e3d55,0xbcf13d62,0xbd6d3cc4,0xbd623cf1,0xbd553d0e,0xbd463d22,0xbd800000,0xbd7f3bc9,0xbd7b3c48,0xbd753c95,
0x3d80,0xbc163d7d,0xbc953d75,0xbcdb3d67,0xbd0e3d55,0xbd2c3d3e,0xbd463d22,0xbd5c3d04,0xbd6d3cc4,0xbd783c79,0xbd7f3bc9,0xbd80bb49,0xbd7bbc48,0xbd71bcac,0xbd62bcf1,0xbd4ebd18,
0xbd35bd35,0xbd18bd4e,0xbcf1bd62,0xbcacbd71,0xbc48bd7b,0xbb49bd80,0x3bc9bd7f,0x3c79bd78,0x3cc4bd6d,0x3d04bd5c,0x3d22bd46,0x3d3ebd2c,0x3d55bd0e,0x3d67bcdb,0x3d75bc95,0x3d7dbc16,
0xbd7b3c48,0xbd7dbc16,0xbd62bcf1,0xbd2cbd3e,0x3d80,0xbcac3d71,0xbd223d46,0xbd5c3d04,0x3d55bd0e,0x3d78bc79,0x3d7f3bc9,0x3d673cdb,0xbcc4bd6d,0xbb49bd80,0x3c95bd75,0x3d18bd4e,
0xbd0e3d55,0xbd4e3d18,0xbd753c95,0xbd80bb49,0x3d353d35,0x3cdb3d67,0x3bc93d7f,0xbc793d78,0x3c48bd7b,0x3d04bd5c,0x3d46bd22,0x3d71bcac,0xbd6dbcc4,0xbd3ebd2c,0xbcf1bd62,0xbc16bd7d,
0x3d6dbcc4,0x3d7d3c16,0x3d463d22,0x3cac3d71,0xbc483d7b,0xbd2c3d3e,0xbd753c95,0xbd78bc79,0x3d80,0xbd043d5c,0xbd623cf1,0xbd80bb49,0xbd55bd0e,0xbcdbbd67,0x3bc9bd7f,0x3d18bd4e,
0xbcc43d6d,0xbd4e3d18,0xbd7f3bc9,0xbd67bcdb,0xbd0ebd55,0xbb49bd80,0x3cf1bd62,0x3d5cbd04,0xbd35bd35,0xbc79bd78,0x3c95bd75,0x3d3ebd2c,0x3d7bbc48,0x3d713cac,0x3d223d46,0x3c163d7d,
0xbd0ebd55,0x3c16bd7d,0x3d46bd22,0x3d803b49,0x3cc43d6d,0xbcac3d71,0xbd623cf1,0xbd78bc79,0xbc48bd7b,0x3d04bd5c,0x3d75bc95,0x3d673cdb,0x3d80,0xbd2c3d3e,0xbd7f3bc9,0xbd4ebd18,
0xbd7bbc48,0xbd18bd4e,0x3bc9bd7f,0x3d3ebd2c,0x3d6d3cc4,0x3cdb3d67,0xbc953d75,0xbd5c3d04,0xbd55bd0e,0xbc79bd78,0x3cf1bd62,0x3d71bcac,0x3d353d35,0x3b493d80,0xbd223d46,0xbd7d3c16,
0xbd35bd35,0x3c16bd7d,0x3d62bcf1,0x3d673cdb,0x3c483d7b,0xbd2c3d3e,0xbd7fbbc9,0xbd04bd5c,0x3cc4bd6d,0x3d78bc79,0x3d463d22,0xbb493d80,0xbd553d0e,0xbd71bcac,0xbc95bd75,0x3d18bd4e,
0x3d80,0xbd4e3d18,0xbd75bc95,0xbcacbd71,0x3d0ebd55,0x3d80bb49,0x3d223d46,0xbc793d78,0xbd6d3cc4,0xbd5cbd04,0xbbc9bd7f,0x3d3ebd2c,0x3d7b3c48,0x3cdb3d67,0xbcf13d62,0xbd7d3c16,
0x3d0ebd55,0x3d7d3c16,0x3c953d75,0xbd3e3d2c,0x3d353d35,0xbcac3d71,0xbd7f3bc9,0xbd04bd5c,0xbc483d7b,0xbd783c79,0xbd22bd46,0x3cdbbd67,0xbd6dbcc4,0xbb49bd80,0x3d62bcf1,0x3d4e3d18,
0x3d7bbc48,0x3d183d4e,0xbcf13d62,0xbd80bb49,0x3d80,0xbd673cdb,0xbd46bd22,0x3c79bd78,0xbd553d0e,0xbd5cbd04,0x3bc9bd7f,0x3d71bcac,0xbcc4bd6d,0x3d2cbd3e,0x3d753c95,0x3c163d7d,
0xbcc43d6d,0xbd7dbc16,0xbbc9bd7f,0x3d71bcac,0x3d0e3d55,0xbd2c3d3e,0xbd62bcf1,0x3c79bd78,0xbd35bd35,0x3d04bd5c,0x3d753c95,0xbb493d80,0xbd7b3c48,0xbcdbbd67,0x3d46bd22,0x3d4e3d18,
0x3d6dbcc4,0x3d183d4e,0xbd223d46,0xbd67bcdb,0x3c48bd7b,0x3d80bb49,0x3c953d75,0xbd5c3d04,0x3d80,0xbd783c79,0xbcf1bd62,0x3d3ebd2c,0x3d553d0e,0xbcac3d71,0xbd7fbbc9,0xbc16bd7d,
0x3d7b3c48,0xbc163d7d,0xbd7fbbc9,0x3b49bd80,0x3d6d3cc4,0xbcac3d71,0xbd75bc95,0x3c79bd78,0x3d553d0e,0xbd043d5c,0xbd62bcf1,0x3cdbbd67,0x3d353d35,0xbd2c3d3e,0xbd46bd22,0x3d18bd4e,
0x3d0e3d55,0xbd4e3d18,0xbd22bd46,0x3d3ebd2c,0x3cc43d6d,0xbd673cdb,0xbcf1bd62,0x3d5cbd04,0x3c483d7b,0xbd783c79,0xbc95bd75,0x3d71bcac,0x3d80,0xbd803b49,0xbbc9bd7f,0x3d7dbc16,
0xbd800000,0xbd7dbc16,0xbd75bc95,0xbd67bcdb,0xbd55bd0e,0xbd3ebd2c,0xbd22bd46,0xbd04bd5c,0xbcc4bd6d,0xbc79bd78,0xbbc9bd7f,0x3b49bd80,0x3c48bd7b,0x3cacbd71,0x3cf1bd62,0x3d18bd4e,
0x3d35bd35,0x3d4ebd18,0x3d62bcf1,0x3d71bcac,0x3d7bbc48,0x3d80bb49,0x3d7f3bc9,0x3d783c79,0x3d6d3cc4,0x3d5c3d04,0x3d463d22,0x3d2c3d3e,0x3d0e3d55,0x3cdb3d67,0x3c953d75,0x3c163d7d,
0xbc48bd7b,0x3c16bd7d,0x3cf1bd62,0x3d3ebd2c,0xbd800000,0xbd71bcac,0xbd46bd22,0xbd04bd5c,0x3d0e3d55,0x3c793d78,0xbbc93d7f,0xbcdb3d67,0x3d6dbcc4,0x3d80bb49,0x3d753c95,0x3d4e3d18,
0xbd55bd0e,0xbd18bd4e,0xbc95bd75,0x3b49bd80,0xbd353d35,0xbd673cdb,0xbd7f3bc9,0xbd78bc79,0x3d7b3c48,0x3d5c3d04,0x3d223d46,0x3cac3d71,0x3cc4bd6d,0x3d2cbd3e,0x3d62bcf1,0x3d7dbc16,
0x3cc43d6d,0xbc163d7d,0xbd223d46,0xbd713cac,0xbd7bbc48,0xbd3ebd2c,0xbc95bd75,0x3c79bd78,0xbd800000,0xbd5cbd04,0xbcf1bd62,0x3b49bd80,0x3d0ebd55,0x3d67bcdb,0x3d7f3bc9,0x3d4e3d18,
0xbd6dbcc4,0xbd18bd4e,0xbbc9bd7f,0x3cdbbd67,0x3d55bd0e,0x3d80bb49,0x3d623cf1,0x3d043d5c,0x3d35bd35,0x3d78bc79,0x3d753c95,0x3d2c3d3e,0x3c483d7b,0xbcac3d71,0xbd463d22,0xbd7d3c16,
0x3d55bd0e,0x3d7d3c16,0x3d223d46,0xbb493d80,0xbd6d3cc4,0xbd71bcac,0xbcf1bd62,0x3c79bd78,0x3d7bbc48,0x3d5c3d04,0x3c953d75,0xbcdb3d67,0xbd800000,0xbd3ebd2c,0xbbc9bd7f,0x3d18bd4e,
0x3c48bd7b,0x3d4ebd18,0x3d7f3bc9,0x3d2c3d3e,0xbcc43d6d,0xbd673cdb,0xbd75bc95,0xbd04bd5c,0x3d0ebd55,0x3d78bc79,0x3d623cf1,0x3cac3d71,0xbd353d35,0xbd803b49,0xbd46bd22,0xbc16bd7d,
0x3d35bd35,0x3d7d3c16,0x3cf13d62,0xbcdb3d67,0xbd7b3c48,0xbd3ebd2c,0x3bc9bd7f,0x3d5cbd04,0x3d6d3cc4,0x3c793d78,0xbd223d46,0xbd80bb49,0xbd0ebd55,0x3cacbd71,0x3d75bc95,0x3d4e3d18,
0xbd800000,0xbd18bd4e,0x3c95bd75,0x3d71bcac,0x3d553d0e,0x3b493d80,0xbd463d22,0xbd78bc79,0xbcc4bd6d,0x3d04bd5c,0x3d7fbbc9,0x3d2c3d3e,0xbc483d7b,0xbd673cdb,0xbd62bcf1,0xbc16bd7d,
0x3d553d0e,0xbc163d7d,0xbd753c95,0xbd2cbd3e,0xbd353d35,0xbd71bcac,0xbbc9bd7f,0x3d5cbd04,0xbd7bbc48,0xbc79bd78,0x3d46bd22,0x3d673cdb,0x3cc4bd6d,0x3d80bb49,0x3cf13d62,0xbd183d4e,
0x3c483d7b,0xbd4e3d18,0xbd62bcf1,0x3b49bd80,0xbd800000,0xbcdbbd67,0x3d22bd46,0x3d783c79,0xbd0ebd55,0x3d04bd5c,0x3d7f3bc9,0x3cac3d71,0x3d6dbcc4,0x3d3e3d2c,0xbc953d75,0xbd7d3c16,
0xbd6dbcc4,0x3c16bd7d,0x3d7fbbc9,0x3cac3d71,0xbd553d0e,0xbd3ebd2c,0x3cf1bd62,0x3d783c79,0x3d35bd35,0x3d5c3d04,0xbc953d75,0xbd80bb49,0xbc48bd7b,0x3d67bcdb,0x3d223d46,0xbd183d4e,
0x3cc43d6d,0xbd4e3d18,0xbd46bd22,0x3cdbbd67,0x3d7b3c48,0x3b493d80,0xbd753c95,0xbd04bd5c,0xbd800000,0xbc79bd78,0x3d62bcf1,0x3d2c3d3e,0xbd0e3d55,0xbd71bcac,0x3bc9bd7f,0x3d7dbc16,
0xbc483d7b,0xbd7dbc16,0x3bc9bd7f,0x3d803b49,0xbcc43d6d,0xbd71bcac,0x3c95bd75,0x3d783c79,0xbd0e3d55,0xbd5cbd04,0x3cf1bd62,0x3d673cdb,0xbd353d35,0xbd3ebd2c,0x3d22bd46,0x3d4e3d18,
0xbd553d0e,0xbd18bd4e,0x3d46bd22,0x3d2c3d3e,0xbd6d3cc4,0xbcdbbd67,0x3d62bcf1,0x3d043d5c,0xbd7b3c48,0xbc79bd78,0x3d75bc95,0x3cac3d71,0xbd800000,0xbb49bd80,0x3d7fbbc9,0x3c163d7d,
0x3d80,0xbd7dbc16,0x3c95bd75,0x3d673cdb,0xbd0e3d55,0xbd3ebd2c,0x3d46bd22,0x3d043d5c,0xbd6d3cc4,0xbc79bd78,0x3d7fbbc9,0xbb493d80,0xbd7bbc48,0x3cacbd71,0x3d623cf1,0xbd183d4e,
0xbd35bd35,0x3d4ebd18,0x3cf13d62,0xbd713cac,0xbc48bd7b,0x3d80bb49,0xbbc93d7f,0xbd78bc79,0x3cc4bd6d,0x3d5c3d04,0xbd223d46,0xbd2cbd3e,0x3d55bd0e,0x3cdb3d67,0xbd753c95,0xbc16bd7d,
0xbd7b3c48,0x3c16bd7d,0x3d623cf1,0xbd3e3d2c,0x3d80,0xbd71bcac,0x3d22bd46,0x3d043d5c,0x3d55bd0e,0x3c793d78,0xbd7fbbc9,0x3cdbbd67,0xbcc4bd6d,0x3d80bb49,0xbc953d75,0xbd4ebd18,
0xbd0e3d55,0xbd18bd4e,0x3d75bc95,0xbb493d80,0x3d353d35,0xbd673cdb,0xbbc9bd7f,0x3d783c79,0x3c48bd7b,0x3d5c3d04,0xbd463d22,0xbcacbd71,0xbd6dbcc4,0x3d2cbd3e,0x3cf13d62,0xbd7d3c16,
0x3d6dbcc4,0xbc163d7d,0xbd46bd22,0x3d71bcac,0xbc483d7b,0xbd3ebd2c,0x3d75bc95,0xbc793d78,0x3d80,0xbd5cbd04,0x3d62bcf1,0xbb493d80,0xbd55bd0e,0x3d67bcdb,0xbbc93d7f,0xbd4ebd18,
0xbcc43d6d,0xbd18bd4e,0x3d7fbbc9,0xbcdb3d67,0xbd0ebd55,0x3d80bb49,0xbcf13d62,0xbd04bd5c,0xbd35bd35,0x3d78bc79,0xbc953d75,0xbd2cbd3e,0x3d7bbc48,0xbcac3d71,0xbd22bd46,0x3d7dbc16,
0xbd0ebd55,0x3d7d3c16,0xbd463d22,0x3b49bd80,0x3cc43d6d,0xbd71bcac,0x3d62bcf1,0xbc793d78,0xbc48bd7b,0x3d5c3d04,0xbd753c95,0x3cdbbd67,0x3d80,0xbd3ebd2c,0x3d7fbbc9,0xbd183d4e,
0xbd7bbc48,0x3d4ebd18,0xbbc93d7f,0xbd2cbd3e,0x3d6d3cc4,0xbd673cdb,0x3c95bd75,0x3d043d5c,0xbd55bd0e,0x3d78bc79,0xbcf13d62,0xbcacbd71,0x3d353d35,0xbd803b49,0x3d22bd46,0x3c163d7d,
0xbd35bd35,0x3d7d3c16,0xbd623cf1,0x3cdbbd67,0x3c483d7b,0xbd3ebd2c,0x3d7f3bc9,0xbd5c3d04,0x3cc4bd6d,0x3c793d78,0xbd46bd22,0x3d803b49,0xbd553d0e,0x3cacbd71,0x3c953d75,0xbd4ebd18,
0x3d80,0xbd18bd4e,0x3d753c95,0xbd713cac,0x3d0ebd55,0x3b493d80,0xbd22bd46,0x3d783c79,0xbd6d3cc4,0x3d04bd5c,0x3bc93d7f,0xbd2cbd3e,0x3d7b3c48,0xbd673cdb,0x3cf1bd62,0x3c163d7d,
0x3d0ebd55,0xbc163d7d,0xbc95bd75,0x3d2c3d3e,0x3d353d35,0xbd71bcac,0x3d7fbbc9,0xbd5c3d04,0xbc483d7b,0xbc79bd78,0x3d223d46,0xbd67bcdb,0xbd6dbcc4,0x3d80bb49,0xbd623cf1,0x3d18bd4e,
0x3d7bbc48,0xbd4e3d18,0x3cf1bd62,0xbb493d80,0x3d80,0xbcdbbd67,0x3d463d22,0xbd78bc79,0xbd553d0e,0x3d04bd5c,0xbbc93d7f,0xbcacbd71,0xbcc4bd6d,0x3d3e3d2c,0xbd75bc95,0x3d7dbc16,
0xbcc43d6d,0x3c16bd7d,0x3bc93d7f,0xbcacbd71,0x3d0e3d55,0xbd3ebd2c,0x3d623cf1,0xbd78bc79,0xbd35bd35,0x3d5c3d04,0xbd75bc95,0x3d803b49,0xbd7b3c48,0x3d67bcdb,0xbd463d22,0x3d18bd4e,
0x3d6dbcc4,0xbd4e3d18,0x3d22bd46,0xbcdb3d67,0x3c48bd7b,0x3b493d80,0xbc95bd75,0x3d043d5c,0x3d80,0xbc79bd78,0x3cf13d62,0xbd2cbd3e,0x3d553d0e,0xbd71bcac,0x3d7f3bc9,0xbd7d3c16,
0x3d7b3c48,0xbd7dbc16,0x3d7f3bc9,0xbd80bb49,0x3d6d3cc4,0xbd71bcac,0x3d753c95,0xbd78bc79,0x3d553d0e,0xbd5cbd04,0x3d623cf1,0xbd67bcdb,0x3d353d35,0xbd3ebd2c,0x3d463d22,0xbd4ebd18,
0x3d0e3d55,0xbd18bd4e,0x3d223d46,0xbd2cbd3e,0x3cc43d6d,0xbcdbbd67,0x3cf13d62,0xbd04bd5c,0x3c483d7b,0xbc79bd78,0x3c953d75,0xbcacbd71,0x3d80,0xbb49bd80,0x3bc93d7f,0xbc16bd7d,
0xbd800000,0x3c16bd7d,0x3d753c95,0xbcdb3d67,0xbd55bd0e,0x3d2cbd3e,0x3d223d46,0xbd5c3d04,0xbcc4bd6d,0x3d78bc79,0x3bc93d7f,0xbd80bb49,0x3c48bd7b,0x3d713cac,0xbcf13d62,0xbd4ebd18,
0x3d35bd35,0x3d183d4e,0xbd623cf1,0xbcacbd71,0x3d7bbc48,0x3b493d80,0xbd7fbbc9,0x3c79bd78,0x3d6d3cc4,0xbd043d5c,0xbd46bd22,0x3d3ebd2c,0x3d0e3d55,0xbd673cdb,0xbc95bd75,0x3d7dbc16,
0xbc48bd7b,0x3d7d3c16,0xbcf13d62,0xbd2cbd3e,0xbd800000,0x3cacbd71,0x3d463d22,0xbd5c3d04,0x3d0e3d55,0xbd783c79,0x3bc9bd7f,0x3d673cdb,0x3d6dbcc4,0x3b493d80,0xbd75bc95,0x3d18bd4e,
0xbd55bd0e,0x3d4ebd18,0x3c953d75,0xbd80bb49,0xbd353d35,0xbcdbbd67,0x3d7fbbc9,0xbc793d78,0x3d7b3c48,0xbd043d5c,0xbd22bd46,0x3d71bcac,0x3cc4bd6d,0x3d3e3d2c,0xbd623cf1,0xbc16bd7d,
0x3cc43d6d,0xbd7dbc16,0x3d22bd46,0x3cac3d71,0xbd7bbc48,0x3d2cbd3e,0x3c953d75,0xbd78bc79,0xbd800000,0x3d04bd5c,0x3cf13d62,0xbd80bb49,0x3d0ebd55,0x3cdb3d67,0xbd7fbbc9,0x3d18bd4e,
0xbd6dbcc4,0x3d4ebd18,0x3bc93d7f,0xbd67bcdb,0x3d55bd0e,0x3b493d80,0xbd62bcf1,0x3d5cbd04,0x3d35bd35,0x3c793d78,0xbd75bc95,0x3d3ebd2c,0x3c483d7b,0xbd71bcac,0x3d46bd22,0x3c163d7d,
0x3d55bd0e,0xbc163d7d,0xbd22bd46,0x3d803b49,0xbd6d3cc4,0x3cacbd71,0x3cf13d62,0xbd78bc79,0x3d7bbc48,0xbd043d5c,0xbc95bd75,0x3d673cdb,0xbd800000,0x3d2cbd3e,0x3bc93d7f,0xbd4ebd18,
0x3c48bd7b,0x3d183d4e,0xbd7fbbc9,0x3d3ebd2c,0xbcc43d6d,0xbcdbbd67,0x3d753c95,0xbd5c3d04,0x3d0ebd55,0x3c793d78,0xbd62bcf1,0x3d71bcac,0xbd353d35,0xbb49bd80,0x3d463d22,0xbd7d3c16,
0x3d35bd35,0xbc163d7d,0xbcf1bd62,0x3d673cdb,0xbd7b3c48,0x3d2cbd3e,0xbbc93d7f,0xbd04bd5c,0x3d6d3cc4,0xbd783c79,0x3d22bd46,0xbb493d80,0xbd0ebd55,0x3d713cac,0xbd753c95,0x3d18bd4e,
0xbd800000,0x3d4ebd18,0xbc953d75,0xbcacbd71,0x3d553d0e,0xbd803b49,0x3d46bd22,0xbc793d78,0xbcc4bd6d,0x3d5c3d04,0xbd7f3bc9,0x3d3ebd2c,0xbc483d7b,0xbcdbbd67,0x3d623cf1,0xbd7d3c16,
0x3d553d0e,0xbd7dbc16,0x3d75bc95,0xbd3e3d2c,0xbd353d35,0x3cacbd71,0x3bc93d7f,0xbd04bd5c,0xbd7bbc48,0x3d78bc79,0xbd463d22,0x3cdbbd67,0x3cc4bd6d,0x3b493d80,0xbcf1bd62,0x3d4e3d18,
0x3c483d7b,0xbd18bd4e,0x3d623cf1,0xbd80bb49,0xbd800000,0x3d67bcdb,0xbd223d46,0x3c79bd78,0xbd0ebd55,0x3d5c3d04,0xbd7fbbc9,0x3d71bcac,0x3d6dbcc4,0xbd2c3d3e,0x3c95bd75,0x3c163d7d,
0xbd6dbcc4,0x3d7d3c16,0xbd7f3bc9,0x3d71bcac,0xbd553d0e,0x3d2cbd3e,0xbcf13d62,0x3c79bd78,0x3d35bd35,0xbd043d5c,0x3c95bd75,0xbb493d80,0xbc48bd7b,0x3cdb3d67,0xbd22bd46,0x3d4e3d18,
0x3cc43d6d,0xbd18bd4e,0x3d463d22,0xbd67bcdb,0x3d7b3c48,0xbd803b49,0x3d75bc95,0xbd5c3d04,0xbd800000,0x3d78bc79,0xbd623cf1,0x3d3ebd2c,0xbd0e3d55,0x3cacbd71,0xbbc93d7f,0xbc16bd7d,
0xbc483d7b,0x3c16bd7d,0xbbc93d7f,0x3b49bd80,0xbcc43d6d,0x3cacbd71,0xbc953d75,0x3c79bd78,0xbd0e3d55,0x3d04bd5c,0xbcf13d62,0x3cdbbd67,0xbd353d35,0x3d2cbd3e,0xbd223d46,0x3d18bd4e,
0xbd553d0e,0x3d4ebd18,0xbd463d22,0x3d3ebd2c,0xbd6d3cc4,0x3d67bcdb,0xbd623cf1,0x3d5cbd04,0xbd7b3c48,0x3d78bc79,0xbd753c95,0x3d71bcac,0xbd800000,0x3d80bb49,0xbd7f3bc9,0x3d7dbc16,
0x3d80,0x3c16bd7d,0xbc953d75,0x3cdbbd67,0xbd0e3d55,0x3d2cbd3e,0xbd463d22,0x3d5cbd04,0xbd6d3cc4,0x3d78bc79,0xbd7f3bc9,0x3d803b49,0xbd7bbc48,0x3d713cac,0xbd62bcf1,0x3d4e3d18,
0xbd35bd35,0x3d183d4e,0xbcf1bd62,0x3cac3d71,0xbc48bd7b,0x3b493d80,0x3bc9bd7f,0xbc793d78,0x3cc4bd6d,0xbd043d5c,0x3d22bd46,0xbd3e3d2c,0x3d55bd0e,0xbd673cdb,0x3d75bc95,0xbd7d3c16,
0xbd7b3c48,0x3d7d3c16,0xbd62bcf1,0x3d2c3d3e,0x3d80,0x3cacbd71,0xbd223d46,0x3d5cbd04,0x3d55bd0e,0xbd783c79,0x3d7f3bc9,0xbd67bcdb,0xbcc4bd6d,0x3b493d80,0x3c95bd75,0xbd183d4e,
0xbd0e3d55,0x3d4ebd18,0xbd753c95,0x3d803b49,0x3d353d35,0xbcdbbd67,0x3bc93d7f,0x3c79bd78,0x3c48bd7b,0xbd043d5c,0x3d46bd22,0xbd713cac,0xbd6dbcc4,0x3d3e3d2c,0xbcf1bd62,0x3c163d7d,
0x3d6dbcc4,0xbd7dbc16,0x3d463d22,0xbcacbd71,0xbc483d7b,0x3d2cbd3e,0xbd753c95,0x3d783c79,0x3d80,0x3d04bd5c,0xbd623cf1,0x3d803b49,0xbd55bd0e,0x3cdb3d67,0x3bc9bd7f,0xbd183d4e,
0xbcc43d6d,0x3d4ebd18,0xbd7f3bc9,0x3d673cdb,0xbd0ebd55,0x3b493d80,0x3cf1bd62,0xbd5c3d04,0xbd35bd35,0x3c793d78,0x3c95bd75,0xbd3e3d2c,0x3d7bbc48,0xbd71bcac,0x3d223d46,0xbc16bd7d,
0xbd0ebd55,0xbc163d7d,0x3d46bd22,0xbd80bb49,0x3cc43d6d,0x3cacbd71,0xbd623cf1,0x3d783c79,0xbc48bd7b,0xbd043d5c,0x3d75bc95,0xbd67bcdb,0x3d80,0x3d2cbd3e,0xbd7f3bc9,0x3d4e3d18,
0xbd7bbc48,0x3d183d4e,0x3bc9bd7f,0xbd3e3d2c,0x3d6d3cc4,0xbcdbbd67,0xbc953d75,0x3d5cbd04,0xbd55bd0e,0x3c793d78,0x3cf1bd62,0xbd713cac,0x3d353d35,0xbb49bd80,0xbd223d46,0x3d7dbc16,
0xbd35bd35,0xbc163d7d,0x3d62bcf1,0xbd67bcdb,0x3c483d7b,0x3d2cbd3e,0xbd7fbbc9,0x3d043d5c,0x3cc4bd6d,0xbd783c79,0x3d463d22,0x3b49bd80,0xbd553d0e,0x3d713cac,0xbc95bd75,0xbd183d4e,
0x3d80,0x3d4ebd18,0xbd75bc95,0x3cac3d71,0x3d0ebd55,0xbd803b49,0x3d223d46,0x3c79bd78,0xbd6d3cc4,0x3d5c3d04,0xbbc9bd7f,0xbd3e3d2c,0x3d7b3c48,0xbcdbbd67,0xbcf13d62,0x3d7dbc16,
0x3d0ebd55,0xbd7dbc16,0x3c953d75,0x3d3ebd2c,0x3d353d35,0x3cacbd71,0xbd7f3bc9,0x3d043d5c,0xbc483d7b,0x3d78bc79,0xbd22bd46,0xbcdb3d67,0xbd6dbcc4,0x3b493d80,0x3d62bcf1,0xbd4ebd18,
0x3d7bbc48,0xbd18bd4e,0xbcf13d62,0x3d803b49,0x3d80,0x3d67bcdb,0xbd46bd22,0xbc793d78,0xbd553d0e,0x3d5c3d04,0x3bc9bd7f,0xbd713cac,0xbcc4bd6d,0xbd2c3d3e,0x3d753c95,0xbc16bd7d,
0xbcc43d6d,0x3d7d3c16,0xbbc9bd7f,0xbd713cac,0x3d0e3d55,0x3d2cbd3e,0xbd62bcf1,0xbc793d78,0xbd35bd35,0xbd043d5c,0x3d753c95,0x3b49bd80,0xbd7b3c48,0x3cdb3d67,0x3d46bd22,0xbd4ebd18,
0x3d6dbcc4,0xbd18bd4e,0xbd223d46,0x3d673cdb,0x3c48bd7b,0xbd803b49,0x3c953d75,0x3d5cbd04,0x3d80,0x3d78bc79,0xbcf1bd62,0xbd3e3d2c,0x3d553d0e,0x3cacbd71,0xbd7fbbc9,0x3c163d7d,
0x3d7b3c48,0x3c16bd7d,0xbd7fbbc9,0xbb493d80,0x3d6d3cc4,0x3cacbd71,0xbd75bc95,0xbc793d78,0x3d553d0e,0x3d04bd5c,0xbd62bcf1,0xbcdb3d67,0x3d353d35,0x3d2cbd3e,0xbd46bd22,0xbd183d4e,
0x3d0e3d55,0x3d4ebd18,0xbd22bd46,0xbd3e3d2c,0x3cc43d6d,0x3d67bcdb,0xbcf1bd62,0xbd5c3d04,0x3c483d7b,0x3d78bc79,0xbc95bd75,0xbd713cac,0x3d80,0x3d80bb49,0xbbc9bd7f,0xbd7d3c16,
0xbd800000,0x3d7d3c16,0xbd75bc95,0x3d673cdb,0xbd55bd0e,0x3d3e3d2c,0xbd22bd46,0x3d043d5c,0xbcc4bd6d,0x3c793d78,0xbbc9bd7f,0xbb493d80,0x3c48bd7b,0xbcac3d71,0x3cf1bd62,0xbd183d4e,
0x3d35bd35,0xbd4e3d18,0x3d62bcf1,0xbd713cac,0x3d7bbc48,0xbd803b49,0x3d7f3bc9,0xbd78bc79,0x3d6d3cc4,0xbd5cbd04,0x3d463d22,0xbd2cbd3e,0x3d0e3d55,0xbcdbbd67,0x3c953d75,0xbc16bd7d,
0xbc48bd7b,0xbc163d7d,0x3cf1bd62,0xbd3e3d2c,0xbd800000,0x3d713cac,0xbd46bd22,0x3d043d5c,0x3d0e3d55,0xbc79bd78,0xbbc93d7f,0x3cdbbd67,0x3d6dbcc4,0xbd803b49,0x3d753c95,0xbd4ebd18,
0xbd55bd0e,0x3d183d4e,0xbc95bd75,0xbb493d80,0xbd353d35,0x3d67bcdb,0xbd7f3bc9,0x3d783c79,0x3d7b3c48,0xbd5cbd04,0x3d223d46,0xbcacbd71,0x3cc4bd6d,0xbd2c3d3e,0x3d62bcf1,0xbd7d3c16,
0x3cc43d6d,0x3c16bd7d,0xbd223d46,0x3d71bcac,0xbd7bbc48,0x3d3e3d2c,0xbc95bd75,0xbc793d78,0xbd800000,0x3d5c3d04,0xbcf1bd62,0xbb493d80,0x3d0ebd55,0xbd673cdb,0x3d7f3bc9,0xbd4ebd18,
0xbd6dbcc4,0x3d183d4e,0xbbc9bd7f,0xbcdb3d67,0x3d55bd0e,0xbd803b49,0x3d623cf1,0xbd04bd5c,0x3d35bd35,0xbd783c79,0x3d753c95,0xbd2cbd3e,0x3c483d7b,0x3cacbd71,0xbd463d22,0x3d7dbc16,
0x3d55bd0e,0xbd7dbc16,0x3d223d46,0x3b49bd80,0xbd6d3cc4,0x3d713cac,0xbcf1bd62,0xbc793d78,0x3d7bbc48,0xbd5cbd04,0x3c953d75,0x3cdbbd67,0xbd800000,0x3d3e3d2c,0xbbc9bd7f,0xbd183d4e,
0x3c48bd7b,0xbd4e3d18,0x3d7f3bc9,0xbd2cbd3e,0xbcc43d6d,0x3d67bcdb,0xbd75bc95,0x3d043d5c,0x3d0ebd55,0xbd783c79,0x3d623cf1,0xbcacbd71,0xbd353d35,0x3d80bb49,0xbd46bd22,0x3c163d7d,
0x3d35bd35,0xbd7dbc16,0x3cf13d62,0x3cdbbd67,0xbd7b3c48,0x3d3e3d2c,0x3bc9bd7f,0xbd5c3d04,0x3d6d3cc4,0xbc79bd78,0xbd223d46,0x3d803b49,0xbd0ebd55,0xbcac3d71,0x3d75bc95,0xbd4ebd18,
0xbd800000,0x3d183d4e,0x3c95bd75,0xbd713cac,0x3d553d0e,0xbb49bd80,0xbd463d22,0x3d783c79,0xbcc4bd6d,0xbd043d5c,0x3d7fbbc9,0xbd2cbd3e,0xbc483d7b,0x3d67bcdb,0xbd62bcf1,0x3c163d7d,
0x3d553d0e,0x3c16bd7d,0xbd753c95,0x3d2c3d3e,0xbd353d35,0x3d713cac,0xbbc9bd7f,0xbd5c3d04,0xbd7bbc48,0x3c793d78,0x3d46bd22,0xbd67bcdb,0x3cc4bd6d,0xbd803b49,0x3cf13d62,0x3d18bd4e,
0x3c483d7b,0x3d4ebd18,0xbd62bcf1,0xbb493d80,0xbd800000,0x3cdb3d67,0x3d22bd46,0xbd78bc79,0xbd0ebd55,0xbd043d5c,0x3d7f3bc9,0xbcacbd71,0x3d6dbcc4,0xbd3ebd2c,0xbc953d75,0x3d7dbc16,
0xbd6dbcc4,0xbc163d7d,0x3d7fbbc9,0xbcacbd71,0xbd553d0e,0x3d3e3d2c,0x3cf1bd62,0xbd78bc79,0x3d35bd35,0xbd5cbd04,0xbc953d75,0x3d803b49,0xbc48bd7b,0xbd673cdb,0x3d223d46,0x3d18bd4e,
0x3cc43d6d,0x3d4ebd18,0xbd46bd22,0xbcdb3d67,0x3d7b3c48,0xbb49bd80,0xbd753c95,0x3d043d5c,0xbd800000,0x3c793d78,0x3d62bcf1,0xbd2cbd3e,0xbd0e3d55,0x3d713cac,0x3bc9bd7f,0xbd7d3c16,
0xbc483d7b,0x3d7d3c16,0x3bc9bd7f,0xbd80bb49,0xbcc43d6d,0x3d713cac,0x3c95bd75,0xbd78bc79,0xbd0e3d55,0x3d5c3d04,0x3cf1bd62,0xbd67bcdb,0xbd353d35,0x3d3e3d2c,0x3d22bd46,0xbd4ebd18,
0xbd553d0e,0x3d183d4e,0x3d46bd22,0xbd2cbd3e,0xbd6d3cc4,0x3cdb3d67,0x3d62bcf1,0xbd04bd5c,0xbd7b3c48,0x3c793d78,0x3d75bc95,0xbcacbd71,0xbd800000,0x3b493d80,0x3d7fbbc9,0xbc16bd7d,
0x3d80,0x3d7d3c16,0x3c95bd75,0xbd67bcdb,0xbd0e3d55,0x3d3e3d2c,0x3d46bd22,0xbd04bd5c,0xbd6d3cc4,0x3c793d78,0x3d7fbbc9,0x3b49bd80,0xbd7bbc48,0xbcac3d71,0x3d623cf1,0x3d18bd4e,
0xbd35bd35,0xbd4e3d18,0x3cf13d62,0x3d71bcac,0xbc48bd7b,0xbd803b49,0xbbc93d7f,0x3d783c79,0x3cc4bd6d,0xbd5cbd04,0xbd223d46,0x3d2c3d3e,0x3d55bd0e,0xbcdbbd67,0xbd753c95,0x3c163d7d,
0xbd7b3c48,0xbc163d7d,0x3d623cf1,0x3d3ebd2c,0x3d80,0x3d713cac,0x3d22bd46,0xbd04bd5c,0x3d55bd0e,0xbc79bd78,0xbd7fbbc9,0xbcdb3d67,0xbcc4bd6d,0xbd803b49,0xbc953d75,0x3d4e3d18,
0xbd0e3d55,0x3d183d4e,0x3d75bc95,0x3b49bd80,0x3d353d35,0x3d67bcdb,0xbbc9bd7f,0xbd78bc79,0x3c48bd7b,0xbd5cbd04,0xbd463d22,0x3cac3d71,0xbd6dbcc4,0xbd2c3d3e,0x3cf13d62,0x3d7dbc16,
0x3d6dbcc4,0x3c16bd7d,0xbd46bd22,0xbd713cac,0xbc483d7b,0x3d3e3d2c,0x3d75bc95,0x3c79bd78,0x3d80,0x3d5c3d04,0x3d62bcf1,0x3b49bd80,0xbd55bd0e,0xbd673cdb,0xbbc93d7f,0x3d4e3d18,
0xbcc43d6d,0x3d183d4e,0x3d7fbbc9,0x3cdbbd67,0xbd0ebd55,0xbd803b49,0xbcf13d62,0x3d043d5c,0xbd35bd35,0xbd783c79,0xbc953d75,0x3d2c3d3e,0x3d7bbc48,0x3cacbd71,0xbd22bd46,0xbd7d3c16,
0xbd0ebd55,0xbd7dbc16,0xbd463d22,0xbb493d80,0x3cc43d6d,0x3d713cac,0x3d62bcf1,0x3c79bd78,0xbc48bd7b,0xbd5cbd04,0xbd753c95,0xbcdb3d67,0x3d80,0x3d3e3d2c,0x3d7fbbc9,0x3d18bd4e,
0xbd7bbc48,0xbd4e3d18,0xbbc93d7f,0x3d2c3d3e,0x3d6d3cc4,0x3d67bcdb,0x3c95bd75,0xbd04bd5c,0xbd55bd0e,0xbd783c79,0xbcf13d62,0x3cac3d71,0x3d353d35,0x3d80bb49,0x3d22bd46,0xbc16bd7d,
0xbd35bd35,0xbd7dbc16,0xbd623cf1,0xbcdb3d67,0x3c483d7b,0x3d3e3d2c,0x3d7f3bc9,0x3d5cbd04,0x3cc4bd6d,0xbc79bd78,0xbd46bd22,0xbd80bb49,0xbd553d0e,0xbcac3d71,0x3c953d75,0x3d4e3d18,
0x3d80,0x3d183d4e,0x3d753c95,0x3d71bcac,0x3d0ebd55,0xbb49bd80,0xbd22bd46,0xbd78bc79,0xbd6d3cc4,0xbd043d5c,0x3bc93d7f,0x3d2c3d3e,0x3d7b3c48,0x3d67bcdb,0x3cf1bd62,0xbc16bd7d,
0x3d0ebd55,0x3c16bd7d,0xbc95bd75,0xbd2cbd3e,0x3d353d35,0x3d713cac,0x3d7fbbc9,0x3d5cbd04,0xbc483d7b,0x3c793d78,0x3d223d46,0x3d673cdb,0xbd6dbcc4,0xbd803b49,0xbd623cf1,0xbd183d4e,
0x3d7bbc48,0x3d4ebd18,0x3cf1bd62,0x3b49bd80,0x3d80,0x3cdb3d67,0x3d463d22,0x3d783c79,0xbd553d0e,0xbd043d5c,0xbbc93d7f,0x3cac3d71,0xbcc4bd6d,0xbd3ebd2c,0xbd75bc95,0xbd7d3c16,
0xbcc43d6d,0xbc163d7d,0x3bc93d7f,0x3cac3d71,0x3d0e3d55,0x3d3e3d2c,0x3d623cf1,0x3d783c79,0xbd35bd35,0xbd5cbd04,0xbd75bc95,0xbd80bb49,0xbd7b3c48,0xbd673cdb,0xbd463d22,0xbd183d4e,
0x3d6dbcc4,0x3d4ebd18,0x3d22bd46,0x3cdbbd67,0x3c48bd7b,0xbb49bd80,0xbc95bd75,0xbd04bd5c,0x3d80,0x3c793d78,0x3cf13d62,0x3d2c3d3e,0x3d553d0e,0x3d713cac,0x3d7f3bc9,0x3d7dbc16,
0x3d7b3c48,0x3d7d3c16,0x3d7f3bc9,0x3d803b49,0x3d6d3cc4,0x3d713cac,0x3d753c95,0x3d783c79,0x3d553d0e,0x3d5c3d04,0x3d623cf1,0x3d673cdb,0x3d353d35,0x3d3e3d2c,0x3d463d22,0x3d4e3d18,
0x3d0e3d55,0x3d183d4e,0x3d223d46,0x3d2c3d3e,0x3cc43d6d,0x3cdb3d67,0x3cf13d62,0x3d043d5c,0x3c483d7b,0x3c793d78,0x3c953d75,0x3cac3d71,0x3d80,0x3b493d80,0x3bc93d7f,0x3c163d7d,
0xbd800000,0xbc163d7d,0x3d753c95,0x3cdbbd67,0xbd55bd0e,0xbd2c3d3e,0x3d223d46,0x3d5cbd04,0xbcc4bd6d,0xbd783c79,0x3bc93d7f,0x3d803b49,0x3c48bd7b,0xbd71bcac,0xbcf13d62,0x3d4e3d18,
0x3d35bd35,0xbd18bd4e,0xbd623cf1,0x3cac3d71,0x3d7bbc48,0xbb49bd80,0xbd7fbbc9,0xbc793d78,0x3d6d3cc4,0x3d04bd5c,0xbd46bd22,0xbd3e3d2c,0x3d0e3d55,0x3d67bcdb,0xbc95bd75,0xbd7d3c16,
0xbc48bd7b,0xbd7dbc16,0xbcf13d62,0x3d2c3d3e,0xbd800000,0xbcac3d71,0x3d463d22,0x3d5cbd04,0x3d0e3d55,0x3d78bc79,0x3bc9bd7f,0xbd67bcdb,0x3d6dbcc4,0xbb49bd80,0xbd75bc95,0xbd183d4e,
0xbd55bd0e,0xbd4e3d18,0x3c953d75,0x3d803b49,0xbd353d35,0x3cdb3d67,0x3d7fbbc9,0x3c79bd78,0x3d7b3c48,0x3d04bd5c,0xbd22bd46,0xbd713cac,0x3cc4bd6d,0xbd3ebd2c,0xbd623cf1,0x3c163d7d,
0x3cc43d6d,0x3d7d3c16,0x3d22bd46,0xbcacbd71,0xbd7bbc48,0xbd2c3d3e,0x3c953d75,0x3d783c79,0xbd800000,0xbd043d5c,0x3cf13d62,0x3d803b49,0x3d0ebd55,0xbcdbbd67,0xbd7fbbc9,0xbd183d4e,
0xbd6dbcc4,0xbd4e3d18,0x3bc93d7f,0x3d673cdb,0x3d55bd0e,0xbb49bd80,0xbd62bcf1,0xbd5c3d04,0x3d35bd35,0xbc79bd78,0xbd75bc95,0xbd3e3d2c,0x3c483d7b,0x3d713cac,0x3d46bd22,0xbc16bd7d,
0x3d55bd0e,0x3c16bd7d,0xbd22bd46,0xbd80bb49,0xbd6d3cc4,0xbcac3d71,0x3cf13d62,0x3d783c79,0x3d7bbc48,0x3d04bd5c,0xbc95bd75,0xbd67bcdb,0xbd800000,0xbd2c3d3e,0x3bc93d7f,0x3d4e3d18,
0x3c48bd7b,0xbd18bd4e,0xbd7fbbc9,0xbd3e3d2c,0xbcc43d6d,0x3cdb3d67,0x3d753c95,0x3d5cbd04,0x3d0ebd55,0xbc79bd78,0xbd62bcf1,0xbd713cac,0xbd353d35,0x3b493d80,0x3d463d22,0x3d7dbc16,
0x3d35bd35,0x3c16bd7d,0xbcf1bd62,0xbd67bcdb,0xbd7b3c48,0xbd2c3d3e,0xbbc93d7f,0x3d043d5c,0x3d6d3cc4,0x3d78bc79,0x3d22bd46,0x3b49bd80,0xbd0ebd55,0xbd71bcac,0xbd753c95,0xbd183d4e,
0xbd800000,0xbd4e3d18,0xbc953d75,0x3cac3d71,0x3d553d0e,0x3d80bb49,0x3d46bd22,0x3c79bd78,0xbcc4bd6d,0xbd5cbd04,0xbd7f3bc9,0xbd3e3d2c,0xbc483d7b,0x3cdb3d67,0x3d623cf1,0x3d7dbc16,
0x3d553d0e,0x3d7d3c16,0x3d75bc95,0x3d3ebd2c,0xbd353d35,0xbcac3d71,0x3bc93d7f,0x3d043d5c,0xbd7bbc48,0xbd783c79,0xbd463d22,0xbcdb3d67,0x3cc4bd6d,0xbb49bd80,0xbcf1bd62,0xbd4ebd18,
0x3c483d7b,0x3d183d4e,0x3d623cf1,0x3d803b49,0xbd800000,0xbd673cdb,0xbd223d46,0xbc793d78,0xbd0ebd55,0xbd5cbd04,0xbd7fbbc9,0xbd713cac,0x3d6dbcc4,0x3d2cbd3e,0x3c95bd75,0xbc16bd7d,
0xbd6dbcc4,0xbd7dbc16,0xbd7f3bc9,0xbd713cac,0xbd553d0e,0xbd2c3d3e,0xbcf13d62,0xbc793d78,0x3d35bd35,0x3d04bd5c,0x3c95bd75,0x3b49bd80,0xbc48bd7b,0xbcdbbd67,0xbd22bd46,0xbd4ebd18,
0x3cc43d6d,0x3d183d4e,0x3d463d22,0x3d673cdb,0x3d7b3c48,0x3d80bb49,0x3d75bc95,0x3d5cbd04,0xbd800000,0xbd783c79,0xbd623cf1,0xbd3e3d2c,0xbd0e3d55,0xbcac3d71,0xbbc93d7f,0x3c163d7d,
0xbc483d7b,0xbc163d7d,0xbbc93d7f,0xbb493d80,0xbcc43d6d,0xbcac3d71,0xbc953d75,0xbc793d78,0xbd0e3d55,0xbd043d5c,0xbcf13d62,0xbcdb3d67,0xbd353d35,0xbd2c3d3e,0xbd223d46,0xbd183d4e,
0xbd553d0e,0xbd4e3d18,0xbd463d22,0xbd3e3d2c,0xbd6d3cc4,0xbd673cdb,0xbd623cf1,0xbd5c3d04,0xbd7b3c48,0xbd783c79,0xbd753c95,0xbd713cac,0xbd800000,0xbd803b49,0xbd7f3bc9,0xbd7d3c16,
0x3f003f00,0xbf003f00,0x3f003f00,0xbf003f00,0x3f003f00,0xbf003f00,0x3f003f00,0xbf003f00,0x3f003f00,0xbf003f00,0x3f003f00,0xbf003f00,0x3f003f00,0xbf003f00,0x3f003f00,0xbf003f00,
0x3eff3f00,0xbd490000,0x3ea23eb5,0xbec6beb5,0x3ef53efb,0xbe15bdc8,0x3e713e8e,0xbee2bed5,0x3ee23eed,0xbe71be44,0x3e153e44,0xbef5beed,0x3ec63ed5,0xbea2be8e,0x3d493dc8,0xbeffbefb,
0x3efb3f00,0xbdc80000,0xbdc80000,0xbefbbf00,0x3ed53eed,0xbe8ebe44,0xbe8ebe44,0xbed5beed,0x3e8e3eb5,0xbed5beb5,0xbed5beb5,0xbe8ebeb5,0x3dc83e44,0xbefbbeed,0xbefbbeed,0xbdc8be44,
0x3ef53f00,0xbe150000,0xbee2beb5,0xbe71beb5,0x3ea23ed5,0xbec6be8e,0xbeffbefb,0x3d49bdc8,0x3d493e44,0xbeffbeed,0xbec6beed,0x3ea23e44,0xbe71bdc8,0xbee2befb,0xbe15be8e,0x3ef53ed5,
0x3eed3f00,0xbe440000,0xbeedbf00,0x3e440000,0x3e443eb5,0xbeedbeb5,0xbe44beb5,0x3eed3eb5,0xbe440000,0xbeedbf00,0x3e440000,0x3eed3f00,0xbeedbeb5,0xbe44beb5,0x3eed3eb5,0x3e443eb5,
0x3ee23f00,0xbe710000,0xbe15beb5,0x3ef53eb5,0x3d493e8e,0xbeffbed5,0x3ea23dc8,0x3ec63efb,0xbec6be44,0xbea2beed,0x3eff3eed,0xbd493e44,0xbef5befb,0x3e15bdc8,0x3e713ed5,0xbee2be8e,
0x3ed53f00,0xbe8e0000,0x3e8e0000,0x3ed53f00,0xbdc83e44,0xbefbbeed,0x3efb3eed,0xbdc83e44,0xbefbbeb5,0xbdc8beb5,0x3dc83eb5,0xbefbbeb5,0xbe8ebeed,0x3ed53e44,0xbed5be44,0xbe8ebeed,
0x3ec63f00,0xbea20000,0x3eff3eb5,0x3d493eb5,0xbe713dc8,0xbee2befb,0x3e153ed5,0xbef5be8e,0xbef5beed,0x3e15be44,0xbee2be44,0xbe71beed,0x3d49be8e,0x3eff3ed5,0xbea2befb,0x3ec63dc8,
0x3f00,0xbf000000,0x3f00,0xbf000000,0xbf00,0x3f000000,0xbf00,0x3f000000,0x3f00,0xbf000000,0x3f00,0xbf000000,0xbf00,0x3f000000,0xbf00,0x3f000000,
0xbd493f00,0xbeff0000,0xbec63eb5,0xbea2beb5,0x3e15befb,0x3ef53dc8,0x3ee2be8e,0x3e713ed5,0xbe713eed,0xbee2be44,0xbef53e44,0xbe15beed,0x3ea2bed5,0x3ec63e8e,0x3effbdc8,0x3d493efb,
0xbdc83f00,0xbefb0000,0xbefb0000,0x3dc8bf00,0x3e8ebeed,0x3ed53e44,0x3ed53e44,0xbe8e3eed,0xbed53eb5,0xbe8ebeb5,0xbe8ebeb5,0x3ed5beb5,0x3efbbe44,0x3dc83eed,0x3dc83eed,0xbefb3e44,
0xbe153f00,0xbef50000,0xbe71beb5,0x3ee2beb5,0x3ec6bed5,0x3ea23e8e,0xbd493efb,0xbeff3dc8,0xbeff3e44,0xbd49beed,0x3ea2beed,0x3ec63e44,0x3ee23dc8,0xbe713efb,0xbef53e8e,0xbe15bed5,
0xbe443f00,0xbeed0000,0x3e44bf00,0x3eed0000,0x3eedbeb5,0x3e443eb5,0xbeed3eb5,0xbe44beb5,0xbeed0000,0x3e44bf00,0x3eed0000,0xbe443f00,0x3e443eb5,0xbeed3eb5,0xbe44beb5,0x3eedbeb5,
0xbe713f00,0xbee20000,0x3ef5beb5,0x3e153eb5,0x3effbe8e,0x3d493ed5,0xbec6bdc8,0x3ea2befb,0xbea2be44,0x3ec6beed,0xbd493eed,0xbeff3e44,0xbe153efb,0xbef53dc8,0x3ee2bed5,0x3e713e8e,
0xbe8e3f00,0xbed50000,0x3ed50000,0xbe8e3f00,0x3efbbe44,0xbdc83eed,0x3dc8beed,0x3efbbe44,0xbdc8beb5,0x3efbbeb5,0xbefb3eb5,0xbdc8beb5,0xbed53eed,0xbe8ebe44,0x3e8e3e44,0xbed53eed,
0xbea23f00,0xbec60000,0x3d493eb5,0xbeff3eb5,0x3ee2bdc8,0xbe713efb,0x3ef5bed5,0x3e153e8e,0x3e15beed,0x3ef5be44,0xbe71be44,0x3ee2beed,0xbeff3e8e,0x3d49bed5,0xbec63efb,0xbea2bdc8,
0x3eb53f00,0xbeb50000,0x3eb53f00,0xbeb50000,0xbeb50000,0xbeb5bf00,0xbeb50000,0xbeb5bf00,0xbeb5bf00,0x3eb50000,0xbeb5bf00,0x3eb50000,0x3eb50000,0x3eb53f00,0x3eb50000,0x3eb53f00,
0xbeff3f00,0x3d490000,0xbea23eb5,0x3ec6beb5,0xbef53efb,0x3e15bdc8,0xbe713e8e,0x3ee2bed5,0xbee23eed,0x3e71be44,0xbe153e44,0x3ef5beed,0xbec63ed5,0x3ea2be8e,0xbd493dc8,0x3effbefb,
0xbefb3f00,0x3dc80000,0x3dc80000,0x3efbbf00,0xbed53eed,0x3e8ebe44,0x3e8ebe44,0x3ed5beed,0xbe8e3eb5,0x3ed5beb5,0x3ed5beb5,0x3e8ebeb5,0xbdc83e44,0x3efbbeed,0x3efbbeed,0x3dc8be44,
0xbef53f00,0x3e150000,0x3ee2beb5,0x3e71beb5,0xbea23ed5,0x3ec6be8e,0x3effbefb,0xbd49bdc8,0xbd493e44,0x3effbeed,0x3ec6beed,0xbea23e44,0x3e71bdc8,0x3ee2befb,0x3e15be8e,0xbef53ed5,
0xbeed3f00,0x3e440000,0x3eedbf00,0xbe440000,0xbe443eb5,0x3eedbeb5,0x3e44beb5,0xbeed3eb5,0x3e440000,0x3eedbf00,0xbe440000,0xbeed3f00,0x3eedbeb5,0x3e44beb5,0xbeed3eb5,0xbe443eb5,
0xbee23f00,0x3e710000,0x3e15beb5,0xbef53eb5,0xbd493e8e,0x3effbed5,0xbea23dc8,0xbec63efb,0x3ec6be44,0x3ea2beed,0xbeff3eed,0x3d493e44,0x3ef5befb,0xbe15bdc8,0xbe713ed5,0x3ee2be8e,
0xbed53f00,0x3e8e0000,0xbe8e0000,0xbed53f00,0x3dc83e44,0x3efbbeed,0xbefb3eed,0x3dc83e44,0x3efbbeb5,0x3dc8beb5,0xbdc83eb5,0x3efbbeb5,0x3e8ebeed,0xbed53e44,0x3ed5be44,0x3e8ebeed,
0xbec63f00,0x3ea20000,0xbeff3eb5,0xbd493eb5,0x3e713dc8,0x3ee2befb,0xbe153ed5,0x3ef5be8e,0x3ef5beed,0xbe15be44,0x3ee2be44,0x3e71beed,0xbd49be8e,0xbeff3ed5,0x3ea2befb,0xbec63dc8,
0xbeb53f00,0xbeb50000,0xbeb53f00,0xbeb50000,0x3eb50000,0xbeb53f00,0x3eb50000,0xbeb53f00,0x3eb5bf00,0x3eb50000,0x3eb5bf00,0x3eb50000,0xbeb50000,0x3eb5bf00,0xbeb50000,0x3eb5bf00,
0x3d493f00,0x3eff0000,0x3ec63eb5,0x3ea2beb5,0xbe15befb,0xbef53dc8,0xbee2be8e,0xbe713ed5,0x3e713eed,0x3ee2be44,0x3ef53e44,0x3e15beed,0xbea2bed5,0xbec63e8e,0xbeffbdc8,0xbd493efb,
0x3dc83f00,0x3efb0000,0x3efb0000,0xbdc8bf00,0xbe8ebeed,0xbed53e44,0xbed53e44,0x3e8e3eed,0x3ed53eb5,0x3e8ebeb5,0x3e8ebeb5,0xbed5beb5,0xbefbbe44,0xbdc83eed,0xbdc83eed,0x3efb3e44,
0x3e153f00,0x3ef50000,0x3e71beb5,0xbee2beb5,0xbec6bed5,0xbea23e8e,0x3d493efb,0x3eff3dc8,0x3eff3e44,0x3d49beed,0xbea2beed,0xbec63e44,0xbee23dc8,0x3e713efb,0x3ef53e8e,0x3e15bed5,
0x3e443f00,0x3eed0000,0xbe44bf00,0xbeed0000,0xbeedbeb5,0xbe443eb5,0x3eed3eb5,0x3e44beb5,0x3eed0000,0xbe44bf00,0xbeed0000,0x3e443f00,0xbe443eb5,0x3eed3eb5,0x3e44beb5,0xbeedbeb5,
0x3e713f00,0x3ee20000,0xbef5beb5,0xbe153eb5,0xbeffbe8e,0xbd493ed5,0x3ec6bdc8,0xbea2befb,0x3ea2be44,0xbec6beed,0x3d493eed,0x3eff3e44,0x3e153efb,0x3ef53dc8,0xbee2bed5,0xbe713e8e,
0x3e8e3f00,0x3ed50000,0xbed50000,0x3e8e3f00,0xbefbbe44,0x3dc83eed,0xbdc8beed,0xbefbbe44,0x3dc8beb5,0xbefbbeb5,0x3efb3eb5,0x3dc8beb5,0x3ed53eed,0x3e8ebe44,0xbe8e3e44,0x3ed53eed,
0x3ea23f00,0x3ec60000,0xbd493eb5,0x3eff3eb5,0xbee2bdc8,0x3e713efb,0xbef5bed5,0xbe153e8e,0xbe15beed,0xbef5be44,0x3e71be44,0xbee2beed,0x3eff3e8e,0xbd49bed5,0x3ec63efb,0x3ea2bdc8,
0x3f003f00,0xbf003f00,0x3f003f00,0xbf003f00,0x3f003f00,0xbf003f00,0x3f003f00,0xbf003f00,0x3f003f00,0xbf003f00,0x3f003f00,0xbf003f00,0x3f003f00,0xbf003f00,0x3f003f00,0xbf003f00,
0xbd490000,0xbeffbf00,0xbec6beb5,0xbea2beb5,0xbe15bdc8,0xbef5befb,0xbee2bed5,0xbe71be8e,0xbe71be44,0xbee2beed,0xbef5beed,0xbe15be44,0xbea2be8e,0xbec6bed5,0xbeffbefb,0xbd49bdc8,
0xbefbbf00,0x3dc80000,0x3dc80000,0x3efb3f00,0xbed5beed,0x3e8e3e44,0x3e8e3e44,0x3ed53eed,0xbe8ebeb5,0x3ed53eb5,0x3ed53eb5,0x3e8e3eb5,0xbdc8be44,0x3efb3eed,0x3efb3eed,0x3dc83e44,
0x3e150000,0x3ef53f00,0x3e713eb5,0xbee2beb5,0x3ec63e8e,0x3ea23ed5,0xbd493dc8,0xbeffbefb,0x3eff3eed,0x3d493e44,0xbea2be44,0xbec6beed,0x3ee23efb,0xbe71bdc8,0xbef5bed5,0xbe15be8e,
0x3eed3f00,0xbe440000,0xbeedbf00,0x3e440000,0x3e443eb5,0xbeedbeb5,0xbe44beb5,0x3eed3eb5,0xbe440000,0xbeedbf00,0x3e440000,0x3eed3f00,0xbeedbeb5,0xbe44beb5,0x3eed3eb5,0x3e443eb5,
0xbe710000,0xbee2bf00,0x3ef53eb5,0x3e153eb5,0xbeffbed5,0xbd49be8e,0x3ec63efb,0xbea2bdc8,0xbea2beed,0x3ec63e44,0xbd493e44,0xbeffbeed,0x3e15bdc8,0x3ef53efb,0xbee2be8e,0xbe71bed5,
0xbed5bf00,0x3e8e0000,0xbe8e0000,0xbed5bf00,0x3dc8be44,0x3efb3eed,0xbefbbeed,0x3dc8be44,0x3efb3eb5,0x3dc83eb5,0xbdc8beb5,0x3efb3eb5,0x3e8e3eed,0xbed5be44,0x3ed53e44,0x3e8e3eed,
0x3ea20000,0x3ec63f00,0xbd49beb5,0x3eff3eb5,0x3ee23efb,0xbe713dc8,0x3ef53e8e,0x3e153ed5,0xbe153e44,0xbef5beed,0x3e713eed,0xbee2be44,0xbeffbed5,0x3d49be8e,0xbec6bdc8,0xbea2befb,
0x3f00,0xbf000000,0x3f00,0xbf000000,0xbf00,0x3f000000,0xbf00,0x3f000000,0x3f00,0xbf000000,0x3f00,0xbf000000,0xbf00,0x3f000000,0xbf00,0x3f000000,
0xbeff0000,0x3d49bf00,0xbea2beb5,0x3ec6beb5,0x3ef53dc8,0xbe153efb,0x3e713ed5,0xbee23e8e,0xbee2be44,0x3e71beed,0xbe15beed,0x3ef5be44,0x3ec63e8e,0xbea23ed5,0x3d493efb,0xbeff3dc8,
0x3dc8bf00,0x3efb0000,0x3efb0000,0xbdc83f00,0xbe8e3eed,0xbed5be44,0xbed5be44,0x3e8ebeed,0x3ed5beb5,0x3e8e3eb5,0x3e8e3eb5,0xbed53eb5,0xbefb3e44,0xbdc8beed,0xbdc8beed,0x3efbbe44,
0x3ef50000,0xbe153f00,0xbee23eb5,0xbe71beb5,0xbea2be8e,0x3ec6bed5,0x3effbdc8,0xbd493efb,0x3d493eed,0xbeff3e44,0xbec6be44,0x3ea2beed,0x3e71befb,0x3ee23dc8,0x3e153ed5,0xbef53e8e,
0xbe443f00,0xbeed0000,0x3e44bf00,0x3eed0000,0x3eedbeb5,0x3e443eb5,0xbeed3eb5,0xbe44beb5,0xbeed0000,0x3e44bf00,0x3eed0000,0xbe443f00,0x3e443eb5,0xbeed3eb5,0xbe44beb5,0x3eedbeb5,
0xbee20000,0x3e71bf00,0x3e153eb5,0xbef53eb5,0x3d493ed5,0xbeff3e8e,0x3ea2befb,0x3ec63dc8,0x3ec6beed,0x3ea23e44,0xbeff3e44,0x3d49beed,0xbef53dc8,0x3e15befb,0x3e713e8e,0xbee23ed5,
0x3e8ebf00,0x3ed50000,0xbed50000,0x3e8ebf00,0xbefb3e44,0x3dc8beed,0xbdc83eed,0xbefb3e44,0x3dc83eb5,0xbefb3eb5,0x3efbbeb5,0x3dc83eb5,0x3ed5beed,0x3e8e3e44,0xbe8ebe44,0x3ed5beed,
0x3ec60000,0xbea23f00,0x3effbeb5,0x3d493eb5,0x3e71befb,0x3ee2bdc8,0xbe15be8e,0x3ef5bed5,0xbef53e44,0x3e15beed,0xbee23eed,0xbe71be44,0xbd493ed5,0xbeff3e8e,0x3ea23dc8,0xbec63efb,
0x3eb53f00,0xbeb50000,0x3eb53f00,0xbeb50000,0xbeb50000,0xbeb5bf00,0xbeb50000,0xbeb5bf00,0xbeb5bf00,0x3eb50000,0xbeb5bf00,0x3eb50000,0x3eb50000,0x3eb53f00,0x3eb50000,0x3eb53f00,
0x3d490000,0x3effbf00,0x3ec6beb5,0x3ea2beb5,0x3e15bdc8,0x3ef5befb,0x3ee2bed5,0x3e71be8e,0x3e71be44,0x3ee2beed,0x3ef5beed,0x3e15be44,0x3ea2be8e,0x3ec6bed5,0x3effbefb,0x3d49bdc8,
0x3efbbf00,0xbdc80000,0xbdc80000,0xbefb3f00,0x3ed5beed,0xbe8e3e44,0xbe8e3e44,0xbed53eed,0x3e8ebeb5,0xbed53eb5,0xbed53eb5,0xbe8e3eb5,0x3dc8be44,0xbefb3eed,0xbefb3eed,0xbdc83e44,
0xbe150000,0xbef53f00,0xbe713eb5,0x3ee2beb5,0xbec63e8e,0xbea23ed5,0x3d493dc8,0x3effbefb,0xbeff3eed,0xbd493e44,0x3ea2be44,0x3ec6beed,0xbee23efb,0x3e71bdc8,0x3ef5bed5,0x3e15be8e,
0xbeed3f00,0x3e440000,0x3eedbf00,0xbe440000,0xbe443eb5,0x3eedbeb5,0x3e44beb5,0xbeed3eb5,0x3e440000,0x3eedbf00,0xbe440000,0xbeed3f00,0x3eedbeb5,0x3e44beb5,0xbeed3eb5,0xbe443eb5,
0x3e710000,0x3ee2bf00,0xbef53eb5,0xbe153eb5,0x3effbed5,0x3d49be8e,0xbec63efb,0x3ea2bdc8,0x3ea2beed,0xbec63e44,0x3d493e44,0x3effbeed,0xbe15bdc8,0xbef53efb,0x3ee2be8e,0x3e71bed5,
0x3ed5bf00,0xbe8e0000,0x3e8e0000,0x3ed5bf00,0xbdc8be44,0xbefb3eed,0x3efbbeed,0xbdc8be44,0xbefb3eb5,0xbdc83eb5,0x3dc8beb5,0xbefb3eb5,0xbe8e3eed,0x3ed5be44,0xbed53e44,0xbe8e3eed,
0xbea20000,0xbec63f00,0x3d49beb5,0xbeff3eb5,0xbee23efb,0x3e713dc8,0xbef53e8e,0xbe153ed5,0x3e153e44,0x3ef5beed,0xbe713eed,0x3ee2be44,0x3effbed5,0xbd49be8e,0x3ec6bdc8,0x3ea2befb,
0xbeb53f00,0xbeb50000,0xbeb53f00,0xbeb50000,0x3eb50000,0xbeb53f00,0x3eb50000,0xbeb53f00,0x3eb5bf00,0x3eb50000,0x3eb5bf00,0x3eb50000,0xbeb50000,0x3eb5bf00,0xbeb50000,0x3eb5bf00,
0x3eff0000,0xbd49bf00,0x3ea2beb5,0xbec6beb5,0xbef53dc8,0x3e153efb,0xbe713ed5,0x3ee23e8e,0x3ee2be44,0xbe71beed,0x3e15beed,0xbef5be44,0xbec63e8e,0x3ea23ed5,0xbd493efb,0x3eff3dc8,
0xbdc8bf00,0xbefb0000,0xbefb0000,0x3dc83f00,0x3e8e3eed,0x3ed5be44,0x3ed5be44,0xbe8ebeed,0xbed5beb5,0xbe8e3eb5,0xbe8e3eb5,0x3ed53eb5,0x3efb3e44,0x3dc8beed,0x3dc8beed,0xbefbbe44,
0xbef50000,0x3e153f00,0x3ee23eb5,0x3e71beb5,0x3ea2be8e,0xbec6bed5,0xbeffbdc8,0x3d493efb,0xbd493eed,0x3eff3e44,0x3ec6be44,0xbea2beed,0xbe71befb,0xbee23dc8,0xbe153ed5,0x3ef53e8e,
0x3e443f00,0x3eed0000,0xbe44bf00,0xbeed0000,0xbeedbeb5,0xbe443eb5,0x3eed3eb5,0x3e44beb5,0x3eed0000,0xbe44bf00,0xbeed0000,0x3e443f00,0xbe443eb5,0x3eed3eb5,0x3e44beb5,0xbeedbeb5,
0x3ee20000,0xbe71bf00,0xbe153eb5,0x3ef53eb5,0xbd493ed5,0x3eff3e8e,0xbea2befb,0xbec63dc8,0xbec6beed,0xbea23e44,0x3eff3e44,0xbd49beed,0x3ef53dc8,0xbe15befb,0xbe713e8e,0x3ee23ed5,
0xbe8ebf00,0xbed50000,0x3ed50000,0xbe8ebf00,0x3efb3e44,0xbdc8beed,0x3dc83eed,0x3efb3e44,0xbdc83eb5,0x3efb3eb5,0xbefbbeb5,0xbdc83eb5,0xbed5beed,0xbe8e3e44,0x3e8ebe44,0xbed5beed,
0xbec60000,0x3ea23f00,0xbeffbeb5,0xbd493eb5,0xbe71befb,0xbee2bdc8,0x3e15be8e,0xbef5bed5,0x3ef53e44,0xbe15beed,0x3ee23eed,0x3e71be44,0x3d493ed5,0x3eff3e8e,0xbea23dc8,0x3ec63efb,
0x3f003f00,0xbf003f00,0x3f003f00,0xbf003f00,0x3f003f00,0xbf003f00,0x3f003f00,0xbf003f00,0x3f003f00,0xbf003f00,0x3f003f00,0xbf003f00,0x3f003f00,0xbf003f00,0x3f003f00,0xbf003f00,
0xbeffbf00,0x3d490000,0xbea2beb5,0x3ec63eb5,0xbef5befb,0x3e153dc8,0xbe71be8e,0x3ee23ed5,0xbee2beed,0x3e713e44,0xbe15be44,0x3ef53eed,0xbec6bed5,0x3ea23e8e,0xbd49bdc8,0x3eff3efb,
0x3efb3f00,0xbdc80000,0xbdc80000,0xbefbbf00,0x3ed53eed,0xbe8ebe44,0xbe8ebe44,0xbed5beed,0x3e8e3eb5,0xbed5beb5,0xbed5beb5,0xbe8ebeb5,0x3dc83e44,0xbefbbeed,0xbefbbeed,0xbdc8be44,
0xbef5bf00,0x3e150000,0x3ee23eb5,0x3e713eb5,0xbea2bed5,0x3ec63e8e,0x3eff3efb,0xbd493dc8,0xbd49be44,0x3eff3eed,0x3ec63eed,0xbea2be44,0x3e713dc8,0x3ee23efb,0x3e153e8e,0xbef5bed5,
0x3eed3f00,0xbe440000,0xbeedbf00,0x3e440000,0x3e443eb5,0xbeedbeb5,0xbe44beb5,0x3eed3eb5,0xbe440000,0xbeedbf00,0x3e440000,0x3eed3f00,0xbeedbeb5,0xbe44beb5,0x3eed3eb5,0x3e443eb5,
0xbee2bf00,0x3e710000,0x3e153eb5,0xbef5beb5,0xbd49be8e,0x3eff3ed5,0xbea2bdc8,0xbec6befb,0x3ec63e44,0x3ea23eed,0xbeffbeed,0x3d49be44,0x3ef53efb,0xbe153dc8,0xbe71bed5,0x3ee23e8e,
0x3ed53f00,0xbe8e0000,0x3e8e0000,0x3ed53f00,0xbdc83e44,0xbefbbeed,0x3efb3eed,0xbdc83e44,0xbefbbeb5,0xbdc8beb5,0x3dc83eb5,0xbefbbeb5,0xbe8ebeed,0x3ed53e44,0xbed5be44,0xbe8ebeed,
0xbec6bf00,0x3ea20000,0xbeffbeb5,0xbd49beb5,0x3e71bdc8,0x3ee23efb,0xbe15bed5,0x3ef53e8e,0x3ef53eed,0xbe153e44,0x3ee23e44,0x3e713eed,0xbd493e8e,0xbeffbed5,0x3ea23efb,0xbec6bdc8,
0x3f00,0xbf000000,0x3f00,0xbf000000,0xbf00,0x3f000000,0xbf00,0x3f000000,0x3f00,0xbf000000,0x3f00,0xbf000000,0xbf00,0x3f000000,0xbf00,0x3f000000,
0x3d49bf00,0x3eff0000,0x3ec6beb5,0x3ea23eb5,0xbe153efb,0xbef5bdc8,0xbee23e8e,0xbe71bed5,0x3e71beed,0x3ee23e44,0x3ef5be44,0x3e153eed,0xbea23ed5,0xbec6be8e,0xbeff3dc8,0xbd49befb,
0xbdc83f00,0xbefb0000,0xbefb0000,0x3dc8bf00,0x3e8ebeed,0x3ed53e44,0x3ed53e44,0xbe8e3eed,0xbed53eb5,0xbe8ebeb5,0xbe8ebeb5,0x3ed5beb5,0x3efbbe44,0x3dc83eed,0x3dc83eed,0xbefb3e44,
0x3e15bf00,0x3ef50000,0x3e713eb5,0xbee23eb5,0xbec63ed5,0xbea2be8e,0x3d49befb,0x3effbdc8,0x3effbe44,0x3d493eed,0xbea23eed,0xbec6be44,0xbee2bdc8,0x3e71befb,0x3ef5be8e,0x3e153ed5,
0xbe443f00,0xbeed0000,0x3e44bf00,0x3eed0000,0x3eedbeb5,0x3e443eb5,0xbeed3eb5,0xbe44beb5,0xbeed0000,0x3e44bf00,0x3eed0000,0xbe443f00,0x3e443eb5,0xbeed3eb5,0xbe44beb5,0x3eedbeb5,
0x3e71bf00,0x3ee20000,0xbef53eb5,0xbe15beb5,0xbeff3e8e,0xbd49bed5,0x3ec63dc8,0xbea23efb,0x3ea23e44,0xbec63eed,0x3d49beed,0x3effbe44,0x3e15befb,0x3ef5bdc8,0xbee23ed5,0xbe71be8e,
0xbe8e3f00,0xbed50000,0x3ed50000,0xbe8e3f00,0x3efbbe44,0xbdc83eed,0x3dc8beed,0x3efbbe44,0xbdc8beb5,0x3efbbeb5,0xbefb3eb5,0xbdc8beb5,0xbed53eed,0xbe8ebe44,0x3e8e3e44,0xbed53eed,
0x3ea2bf00,0x3ec60000,0xbd49beb5,0x3effbeb5,0xbee23dc8,0x3e71befb,0xbef53ed5,0xbe15be8e,0xbe153eed,0xbef53e44,0x3e713e44,0xbee23eed,0x3effbe8e,0xbd493ed5,0x3ec6befb,0x3ea23dc8,
0x3eb53f00,0xbeb50000,0x3eb53f00,0xbeb50000,0xbeb50000,0xbeb5bf00,0xbeb50000,0xbeb5bf00,0xbeb5bf00,0x3eb50000,0xbeb5bf00,0x3eb50000,0x3eb50000,0x3eb53f00,0x3eb50000,0x3eb53f00,
0x3effbf00,0xbd490000,0x3ea2beb5,0xbec63eb5,0x3ef5befb,0xbe153dc8,0x3e71be8e,0xbee23ed5,0x3ee2beed,0xbe713e44,0x3e15be44,0xbef53eed,0x3ec6bed5,0xbea23e8e,0x3d49bdc8,0xbeff3efb,
0xbefb3f00,0x3dc80000,0x3dc80000,0x3efbbf00,0xbed53eed,0x3e8ebe44,0x3e8ebe44,0x3ed5beed,0xbe8e3eb5,0x3ed5beb5,0x3ed5beb5,0x3e8ebeb5,0xbdc83e44,0x3efbbeed,0x3efbbeed,0x3dc8be44,
0x3ef5bf00,0xbe150000,0xbee23eb5,0xbe713eb5,0x3ea2bed5,0xbec63e8e,0xbeff3efb,0x3d493dc8,0x3d49be44,0xbeff3eed,0xbec63eed,0x3ea2be44,0xbe713dc8,0xbee23efb,0xbe153e8e,0x3ef5bed5,
0xbeed3f00,0x3e440000,0x3eedbf00,0xbe440000,0xbe443eb5,0x3eedbeb5,0x3e44beb5,0xbeed3eb5,0x3e440000,0x3eedbf00,0xbe440000,0xbeed3f00,0x3eedbeb5,0x3e44beb5,0xbeed3eb5,0xbe443eb5,
0x3ee2bf00,0xbe710000,0xbe153eb5,0x3ef5beb5,0x3d49be8e,0xbeff3ed5,0x3ea2bdc8,0x3ec6befb,0xbec63e44,0xbea23eed,0x3effbeed,0xbd49be44,0xbef53efb,0x3e153dc8,0x3e71bed5,0xbee23e8e,
0xbed53f00,0x3e8e0000,0xbe8e0000,0xbed53f00,0x3dc83e44,0x3efbbeed,0xbefb3eed,0x3dc83e44,0x3efbbeb5,0x3dc8beb5,0xbdc83eb5,0x3efbbeb5,0x3e8ebeed,0xbed53e44,0x3ed5be44,0x3e8ebeed,
0x3ec6bf00,0xbea20000,0x3effbeb5,0x3d49beb5,0xbe71bdc8,0xbee23efb,0x3e15bed5,0xbef53e8e,0xbef53eed,0x3e153e44,0xbee23e44,0xbe713eed,0x3d493e8e,0x3effbed5,0xbea23efb,0x3ec6bdc8,
0xbeb53f00,0xbeb50000,0xbeb53f00,0xbeb50000,0x3eb50000,0xbeb53f00,0x3eb50000,0xbeb53f00,0x3eb5bf00,0x3eb50000,0x3eb5bf00,0x3eb50000,0xbeb50000,0x3eb5bf00,0xbeb50000,0x3eb5bf00,
0xbd49bf00,0xbeff0000,0xbec6beb5,0xbea23eb5,0x3e153efb,0x3ef5bdc8,0x3ee23e8e,0x3e71bed5,0xbe71beed,0xbee23e44,0xbef5be44,0xbe153eed,0x3ea23ed5,0x3ec6be8e,0x3eff3dc8,0x3d49befb,
0x3dc83f00,0x3efb0000,0x3efb0000,0xbdc8bf00,0xbe8ebeed,0xbed53e44,0xbed53e44,0x3e8e3eed,0x3ed53eb5,0x3e8ebeb5,0x3e8ebeb5,0xbed5beb5,0xbefbbe44,0xbdc83eed,0xbdc83eed,0x3efb3e44,
0xbe15bf00,0xbef50000,0xbe713eb5,0x3ee23eb5,0x3ec63ed5,0x3ea2be8e,0xbd49befb,0xbeffbdc8,0xbeffbe44,0xbd493eed,0x3ea23eed,0x3ec6be44,0x3ee2bdc8,0xbe71befb,0xbef5be8e,0xbe153ed5,
0x3e443f00,0x3eed0000,0xbe44bf00,0xbeed0000,0xbeedbeb5,0xbe443eb5,0x3eed3eb5,0x3e44beb5,0x3eed0000,0xbe44bf00,0xbeed0000,0x3e443f00,0xbe443eb5,0x3eed3eb5,0x3e44beb5,0xbeedbeb5,
0xbe71bf00,0xbee20000,0x3ef53eb5,0x3e15beb5,0x3eff3e8e,0x3d49bed5,0xbec63dc8,0x3ea23efb,0xbea23e44,0x3ec63eed,0xbd49beed,0xbeffbe44,0xbe15befb,0xbef5bdc8,0x3ee23ed5,0x3e71be8e,
0x3e8e3f00,0x3ed50000,0xbed50000,0x3e8e3f00,0xbefbbe44,0x3dc83eed,0xbdc8beed,0xbefbbe44,0x3dc8beb5,0xbefbbeb5,0x3efb3eb5,0x3dc8beb5,0x3ed53eed,0x3e8ebe44,0xbe8e3e44,0x3ed53eed,
0xbea2bf00,0xbec60000,0x3d49beb5,0xbeffbeb5,0x3ee23dc8,0xbe71befb,0x3ef53ed5,0x3e15be8e,0x3e153eed,0x3ef53e44,0xbe713e44,0x3ee23eed,0xbeffbe8e,0x3d493ed5,0xbec6befb,0xbea23dc8,
0x3f003f00,0xbf003f00,0x3f003f00,0xbf003f00,0x3f003f00,0xbf003f00,0x3f003f00,0xbf003f00,0x3f003f00,0xbf003f00,0x3f003f00,0xbf003f00,0x3f003f00,0xbf003f00,0x3f003f00,0xbf003f00,
0x3d490000,0x3eff3f00,0x3ec63eb5,0x3ea23eb5,0x3e153dc8,0x3ef53efb,0x3ee23ed5,0x3e713e8e,0x3e713e44,0x3ee23eed,0x3ef53eed,0x3e153e44,0x3ea23e8e,0x3ec63ed5,0x3eff3efb,0x3d493dc8,
0xbefbbf00,0x3dc80000,0x3dc80000,0x3efb3f00,0xbed5beed,0x3e8e3e44,0x3e8e3e44,0x3ed53eed,0xbe8ebeb5,0x3ed53eb5,0x3ed53eb5,0x3e8e3eb5,0xbdc8be44,0x3efb3eed,0x3efb3eed,0x3dc83e44,
0xbe150000,0xbef5bf00,0xbe71beb5,0x3ee23eb5,0xbec6be8e,0xbea2bed5,0x3d49bdc8,0x3eff3efb,0xbeffbeed,0xbd49be44,0x3ea23e44,0x3ec63eed,0xbee2befb,0x3e713dc8,0x3ef53ed5,0x3e153e8e,
0x3eed3f00,0xbe440000,0xbeedbf00,0x3e440000,0x3e443eb5,0xbeedbeb5,0xbe44beb5,0x3eed3eb5,0xbe440000,0xbeedbf00,0x3e440000,0x3eed3f00,0xbeedbeb5,0xbe44beb5,0x3eed3eb5,0x3e443eb5,
0x3e710000,0x3ee23f00,0xbef5beb5,0xbe15beb5,0x3eff3ed5,0x3d493e8e,0xbec6befb,0x3ea23dc8,0x3ea23eed,0xbec6be44,0x3d49be44,0x3eff3eed,0xbe153dc8,0xbef5befb,0x3ee23e8e,0x3e713ed5,
0xbed5bf00,0x3e8e0000,0xbe8e0000,0xbed5bf00,0x3dc8be44,0x3efb3eed,0xbefbbeed,0x3dc8be44,0x3efb3eb5,0x3dc83eb5,0xbdc8beb5,0x3efb3eb5,0x3e8e3eed,0xbed5be44,0x3ed53e44,0x3e8e3eed,
0xbea20000,0xbec6bf00,0x3d493eb5,0xbeffbeb5,0xbee2befb,0x3e71bdc8,0xbef5be8e,0xbe15bed5,0x3e15be44,0x3ef53eed,0xbe71beed,0x3ee23e44,0x3eff3ed5,0xbd493e8e,0x3ec63dc8,0x3ea23efb,
0x3f00,0xbf000000,0x3f00,0xbf000000,0xbf00,0x3f000000,0xbf00,0x3f000000,0x3f00,0xbf000000,0x3f00,0xbf000000,0xbf00,0x3f000000,0xbf00,0x3f000000,
0x3eff0000,0xbd493f00,0x3ea23eb5,0xbec63eb5,0xbef5bdc8,0x3e15befb,0xbe71bed5,0x3ee2be8e,0x3ee23e44,0xbe713eed,0x3e153eed,0xbef53e44,0xbec6be8e,0x3ea2bed5,0xbd49befb,0x3effbdc8,
0x3dc8bf00,0x3efb0000,0x3efb0000,0xbdc83f00,0xbe8e3eed,0xbed5be44,0xbed5be44,0x3e8ebeed,0x3ed5beb5,0x3e8e3eb5,0x3e8e3eb5,0xbed53eb5,0xbefb3e44,0xbdc8beed,0xbdc8beed,0x3efbbe44,
0xbef50000,0x3e15bf00,0x3ee2beb5,0x3e713eb5,0x3ea23e8e,0xbec63ed5,0xbeff3dc8,0x3d49befb,0xbd49beed,0x3effbe44,0x3ec63e44,0xbea23eed,0xbe713efb,0xbee2bdc8,0xbe15bed5,0x3ef5be8e,
0xbe443f00,0xbeed0000,0x3e44bf00,0x3eed0000,0x3eedbeb5,0x3e443eb5,0xbeed3eb5,0xbe44beb5,0xbeed0000,0x3e44bf00,0x3eed0000,0xbe443f00,0x3e443eb5,0xbeed3eb5,0xbe44beb5,0x3eedbeb5,
0x3ee20000,0xbe713f00,0xbe15beb5,0x3ef5beb5,0xbd49bed5,0x3effbe8e,0xbea23efb,0xbec6bdc8,0xbec63eed,0xbea2be44,0x3effbe44,0xbd493eed,0x3ef5bdc8,0xbe153efb,0xbe71be8e,0x3ee2bed5,
0x3e8ebf00,0x3ed50000,0xbed50000,0x3e8ebf00,0xbefb3e44,0x3dc8beed,0xbdc83eed,0xbefb3e44,0x3dc83eb5,0xbefb3eb5,0x3efbbeb5,0x3dc83eb5,0x3ed5beed,0x3e8e3e44,0xbe8ebe44,0x3ed5beed,
0xbec60000,0x3ea2bf00,0xbeff3eb5,0xbd49beb5,0xbe713efb,0xbee23dc8,0x3e153e8e,0xbef53ed5,0x3ef5be44,0xbe153eed,0x3ee2beed,0x3e713e44,0x3d49bed5,0x3effbe8e,0xbea2bdc8,0x3ec6befb,
0x3eb53f00,0xbeb50000,0x3eb53f00,0xbeb50000,0xbeb50000,0xbeb5bf00,0xbeb50000,0xbeb5bf00,0xbeb5bf00,0x3eb50000,0xbeb5bf00,0x3eb50000,0x3eb50000,0x3eb53f00,0x3eb50000,0x3eb53f00,
0xbd490000,0xbeff3f00,0xbec63eb5,0xbea23eb5,0xbe153dc8,0xbef53efb,0xbee23ed5,0xbe713e8e,0xbe713e44,0xbee23eed,0xbef53eed,0xbe153e44,0xbea23e8e,0xbec63ed5,0xbeff3efb,0xbd493dc8,
0x3efbbf00,0xbdc80000,0xbdc80000,0xbefb3f00,0x3ed5beed,0xbe8e3e44,0xbe8e3e44,0xbed53eed,0x3e8ebeb5,0xbed53eb5,0xbed53eb5,0xbe8e3eb5,0x3dc8be44,0xbefb3eed,0xbefb3eed,0xbdc83e44,
0x3e150000,0x3ef5bf00,0x3e71beb5,0xbee23eb5,0x3ec6be8e,0x3ea2bed5,0xbd49bdc8,0xbeff3efb,0x3effbeed,0x3d49be44,0xbea23e44,0xbec63eed,0x3ee2befb,0xbe713dc8,0xbef53ed5,0xbe153e8e,
0xbeed3f00,0x3e440000,0x3eedbf00,0xbe440000,0xbe443eb5,0x3eedbeb5,0x3e44beb5,0xbeed3eb5,0x3e440000,0x3eedbf00,0xbe440000,0xbeed3f00,0x3eedbeb5,0x3e44beb5,0xbeed3eb5,0xbe443eb5,
0xbe710000,0xbee23f00,0x3ef5beb5,0x3e15beb5,0xbeff3ed5,0xbd493e8e,0x3ec6befb,0xbea23dc8,0xbea23eed,0x3ec6be44,0xbd49be44,0xbeff3eed,0x3e153dc8,0x3ef5befb,0xbee23e8e,0xbe713ed5,
0x3ed5bf00,0xbe8e0000,0x3e8e0000,0x3ed5bf00,0xbdc8be44,0xbefb3eed,0x3efbbeed,0xbdc8be44,0xbefb3eb5,0xbdc83eb5,0x3dc8beb5,0xbefb3eb5,0xbe8e3eed,0x3ed5be44,0xbed53e44,0xbe8e3eed,
0x3ea20000,0x3ec6bf00,0xbd493eb5,0x3effbeb5,0x3ee2befb,0xbe71bdc8,0x3ef5be8e,0x3e15bed5,0xbe15be44,0xbef53eed,0x3e71beed,0xbee23e44,0xbeff3ed5,0x3d493e8e,0xbec63dc8,0xbea23efb,
0xbeb53f00,0xbeb50000,0xbeb53f00,0xbeb50000,0x3eb50000,0xbeb53f00,0x3eb50000,0xbeb53f00,0x3eb5bf00,0x3eb50000,0x3eb5bf00,0x3eb50000,0xbeb50000,0x3eb5bf00,0xbeb50000,0x3eb5bf00,
0xbeff0000,0x3d493f00,0xbea23eb5,0x3ec63eb5,0x3ef5bdc8,0xbe15befb,0x3e71bed5,0xbee2be8e,0xbee23e44,0x3e713eed,0xbe153eed,0x3ef53e44,0x3ec6be8e,0xbea2bed5,0x3d49befb,0xbeffbdc8,
0xbdc8bf00,0xbefb0000,0xbefb0000,0x3dc83f00,0x3e8e3eed,0x3ed5be44,0x3ed5be44,0xbe8ebeed,0xbed5beb5,0xbe8e3eb5,0xbe8e3eb5,0x3ed53eb5,0x3efb3e44,0x3dc8beed,0x3dc8beed,0xbefbbe44,
0x3ef50000,0xbe15bf00,0xbee2beb5,0xbe713eb5,0xbea23e8e,0x3ec63ed5,0x3eff3dc8,0xbd49befb,0x3d49beed,0xbeffbe44,0xbec63e44,0x3ea23eed,0x3e713efb,0x3ee2bdc8,0x3e15bed5,0xbef5be8e,
0x3e443f00,0x3eed0000,0xbe44bf00,0xbeed0000,0xbeedbeb5,0xbe443eb5,0x3eed3eb5,0x3e44beb5,0x3eed0000,0xbe44bf00,0xbeed0000,0x3e443f00,0xbe443eb5,0x3eed3eb5,0x3e44beb5,0xbeedbeb5,
0xbee20000,0x3e713f00,0x3e15beb5,0xbef5beb5,0x3d49bed5,0xbeffbe8e,0x3ea23efb,0x3ec6bdc8,0x3ec63eed,0x3ea2be44,0xbeffbe44,0x3d493eed,0xbef5bdc8,0x3e153efb,0x3e71be8e,0xbee2bed5,
0xbe8ebf00,0xbed50000,0x3ed50000,0xbe8ebf00,0x3efb3e44,0xbdc8beed,0x3dc83eed,0x3efb3e44,0xbdc83eb5,0x3efb3eb5,0xbefbbeb5,0xbdc83eb5,0xbed5beed,0xbe8e3e44,0x3e8ebe44,0xbed5beed,
0x3ec60000,0xbea2bf00,0x3eff3eb5,0x3d49beb5,0x3e713efb,0x3ee23dc8,0xbe153e8e,0x3ef53ed5,0xbef5be44,0x3e153eed,0xbee2beed,0xbe713e44,0xbd49bed5,0xbeffbe8e,0x3ea2bdc8,0xbec6befb,
0x3f800000,0x0,0x3f800000,0x0,0x3f800000,0x0,0x3f800000,0x0,0x3f800000,0x0,0x3f800000,0x0,0x3f800000,0x0,0x3f800000,0x0,
0x3f800000,0x0,0x3f7fec43,0xbcc90ab0,0x3f7fb10f,0xbd48fb30,0x3f7f4e6d,0xbd96a905,0x3f7ec46d,0xbdc8bd36,0x3f7e1324,0xbdfab273,0x3f7d3aac,0xbe164083,0x3f7c3b28,0xbe2f10a2,
0x3f800000,0x0,0x3f7ffec4,0xbbc90f88,0x3f7ffb11,0xbc490e90,0x3f7ff4e6,0xbc96c9b6,0x3f7fec43,0xbcc90ab0,0x3f7fe129,0xbcfb49ba,0x3f7fd397,0xbd16c32c,0x3f7fc38f,0xbd2fe007,
0x3f800000,0x0,0x3f7fe129,0xbcfb49ba,0x3f7f84ab,0xbd7b2b74,0x3f7eea9d,0xbdbc3ac3,0x3f7e1324,0xbdfab273,0x3f7cfe73,0xbe1c76de,0x3f7baccd,0xbe3b6ecf,0x3f7a1e84,0xbe5a3997,
0x3f800000,0x0,0x3f7ffb11,0xbc490e90,0x3f7fec43,0xbcc90ab0,0x3f7fd397,0xbd16c32c,0x3f7fb10f,0xbd48fb30,0x3f7f84ab,0xbd7b2b74,0x3f7f4e6d,0xbd96a905,0x3f7f0e58,0xbdafb680,
0x3f800000,0x0,0x3f7fd397,0xbd16c32c,0x3f7f4e6d,0xbd96a905,0x3f7e70b0,0xbde1bc2e,0x3f7d3aac,0xbe164083,0x3f7baccd,0xbe3b6ecf,0x3f79c79d,0xbe605c13,0x3f778bc5,0xbe827dc0,
0x3f800000,0x0,0x3f7ff4e6,0xbc96c9b6,0x3f7fd397,0xbd16c32c,0x3f7f9c18,0xbd621469,0x3f7f4e6d,0xbd96a905,0x3f7eea9d,0xbdbc3ac3,0x3f7e70b0,0xbde1bc2e,0x3f7de0b1,0xbe039502,
0x3f800000,0x0,0x3f7fc38f,0xbd2fe007,0x3f7f0e58,0xbdafb680,0x3f7de0b1,0xbe039502,0x3f7c3b28,0xbe2f10a2,0x3f7a1e84,0xbe5a3997,0x3f778bc5,0xbe827dc0,0x3f748422,0xbe97a117,
0x3f800000,0x0,0x3f7fb10f,0xbd48fb30,0x3f7ec46d,0xbdc8bd36,0x3f7d3aac,0xbe164083,0x3f7b14be,0xbe47c5c2,0x3f7853f8,0xbe78cfcc,0x3f74fa0b,0xbe94a031,0x3f710908,0xbeac7cd4,
0x3f800000,0x0,0x3f7f4e6d,0xbd96a905,0x3f7d3aac,0xbe164083,0x3f79c79d,0xbe605c13,0x3f74fa0b,0xbe94a031,0x3f6ed89e,0xbeb8442a,0x3f676bd8,0xbedae880,0x3f5ebe05,0xbefc5d27,
0x3f800000,0x0,0x3f7f9c18,0xbd621469,0x3f7e70b0,0xbde1bc2e,0x3f7c7eb0,0xbe28defc,0x3f79c79d,0xbe605c13,0x3f764d97,0xbe8b9507,0x3f721352,0xbea68f12,0x3f6d1c1d,0xbec1071e,
0x3f800000,0x0,0x3f7f2f9d,0xbda3308c,0x3f7cbfc9,0xbe22abb6,0x3f78b47b,0xbe72b651,0x3f731447,0xbea09ae5,0x3f6be858,0xbec6d529,0x3f633c5a,0xbeebcbbb,0x3f591e6a,0xbf07a136,
0x3f800000,0x0,0x3f7f84ab,0xbd7b2b74,0x3f7e1324,0xbdfab273,0x3f7baccd,0xbe3b6ecf,0x3f7853f8,0xbe78cfcc,0x3f740bdd,0xbe9aa086,0x3f6ed89e,0xbeb8442a,0x3f68bf3c,0xbed53641,
0x3f800000,0x0,0x3f7f0e58,0xbdafb680,0x3f7c3b28,0xbe2f10a2,0x3f778bc5,0xbe827dc0,0x3f710908,0xbeac7cd4,0x3f68bf3c,0xbed53641,0x3f5ebe05,0xbefc5d27,0x3f531849,0xbf10d3cd,
0x3f800000,0x0,0x3f7f6ac7,0xbd8a200a,0x3f7dabcc,0xbe09cf86,0x3f7ac516,0xbe4dee60,0x3f76ba07,0xbe888e93,0x3f718f57,0xbea986c4,0x3f6b4b0c,0xbec9b953,0x3f63f473,0xbee900b7,
0x3f800000,0x0,0x3f7eea9d,0xbdbc3ac3,0x3f7baccd,0xbe3b6ecf,0x3f764d97,0xbe8b9507,0x3f6ed89e,0xbeb8442a,0x3f655e0b,0xbee363fa,0x3f59f26a,0xbf064b82,0x3f4cae79,0xbf19c200,
0x3f800000,0x0,0x3f7ec46d,0xbdc8bd36,0x3f7b14be,0xbe47c5c2,0x3f74fa0b,0xbe94a031,0x3f6c835e,0xbec3ef15,0x3f61c598,0xbef15aea,0x3f54db31,0xbf0e39da,0x3f45e403,0xbf226799,
0x3f800000,0x0,0x3f7e1324,0xbdfab273,0x3f7853f8,0xbe78cfcc,0x3f6ed89e,0xbeb8442a,0x3f61c598,0xbef15aea,0x3f514d3d,0xbf13682a,0x3f3daef9,0xbf2beb4a,0x3f273656,0xbf41d870,
0x3f800000,0x0,0x3f7e9bc9,0xbdd53db9,0x3f7a7302,0xbe541501,0x3f73913f,0xbe9d9e78,0x3f6a09a7,0xbecf7bca,0x3f5df6be,0xbeff17b2,0x3f4f7a1f,0xbf15f6d9,0x3f3ebc1b,0xbf2ac082,
0x3f800000,0x0,0x3f7de0b1,0xbe039502,0x3f778bc5,0xbe827dc0,0x3f6d1c1d,0xbec1071e,0x3f5ebe05,0xbefc5d27,0x3f4cae79,0xbf19c200,0x3f373a23,0xbf32c8c9,0x3f1ebc12,0xbf48d8b3,
0x3f800000,0x0,0x3f7e70b0,0xbde1bc2e,0x3f79c79d,0xbe605c13,0x3f721352,0xbea68f12,0x3f676bd8,0xbedae880,0x3f59f26a,0xbf064b82,0x3f49d112,0xbf1d7fd1,0x3f373a23,0xbf32c8c9,
0x3f800000,0x0,0x3f7dabcc,0xbe09cf86,0x3f76ba07,0xbe888e93,0x3f6b4b0c,0xbec9b953,0x3f5b941a,0xbf039c3d,0x3f47de65,0xbf1ff6cb,0x3f3085bb,0xbf396842,0x3f15f6d9,0xbf4f7a1f,
0x3f800000,0x0,0x3f7e4323,0xbdee3876,0x3f791298,0xbe6c9a7f,0x3f708066,0xbeaf713a,0x3f64aa59,0xbee63375,0x3f55b993,0xbf0cead0,0x3f43e200,0xbf24d225,0x3f2f61a5,0xbf3a7ca4,
0x3f800000,0x0,0x3f7d7474,0xbe1008b7,0x3f75dec6,0xbe8e9a22,0x3f696591,0xbed25a09,0x3f584853,0xbf08f59b,0x3f42de29,0xbf26050a,0x3f299415,0xbf3fc767,0x3f0cead0,0xbf55b993,
0x3f800000,0x0,0x3f7d3aac,0xbe164083,0x3f74fa0b,0xbe94a031,0x3f676bd8,0xbedae880,0x3f54db31,0xbf0e39da,0x3f3daef9,0xbf2beb4a,0x3f226799,0xbf45e403,0x3f039c3d,0xbf5b941a,
0x3f800000,0x0,0x3f7c3b28,0xbe2f10a2,0x3f710908,0xbeac7cd4,0x3f5ebe05,0xbefc5d27,0x3f45e403,0xbf226799,0x3f273656,0xbf41d870,0x3f039c3d,0xbf5b941a,0x3eb8442a,0xbf6ed89e,
0x3f800000,0x0,0x3f7cfe73,0xbe1c76de,0x3f740bdd,0xbe9aa086,0x3f655e0b,0xbee363fa,0x3f514d3d,0xbf13682a,0x3f385216,0xbf31a81d,0x3f1b02c6,0xbf4bbbf8,0x3ef41f07,0xbf6106f2,
0x3f800000,0x0,0x3f7bf531,0xbe354098,0x3f6ff573,0xbeb263ef,0x3f5c61c7,0xbf0242b1,0x3f41d870,0xbf273656,0x3f212ff9,0xbf46e22a,0x3ef6e0cb,0xbf604621,0x3ea395c5,0xbf7294f8,
0x3f800000,0x0,0x3f7cbfc9,0xbe22abb6,0x3f731447,0xbea09ae5,0x3f633c5a,0xbeebcbbb,0x3f4d9f02,0xbf187fc0,0x3f32c8c9,0xbf373a23,0x3f13682a,0xbf514d3d,0x3ee0924f,0xbf660f88,
0x3f800000,0x0,0x3f7baccd,0xbe3b6ecf,0x3f6ed89e,0xbeb8442a,0x3f59f26a,0xbf064b82,0x3f3daef9,0xbf2beb4a,0x3f1b02c6,0xbf4bbbf8,0x3ee63375,0xbf64aa59,0x3e8e9a22,0xbf75dec6,
0x3f800000,0x0,0x3f7c7eb0,0xbe28defc,0x3f721352,0xbea68f12,0x3f6106f2,0xbef41f07,0x3f49d112,0xbf1d7fd1,0x3f2d1469,0xbf3ca003,0x3f0b9a6b,0xbf5695e5,0x3ecc9b8b,0xbf6aab7b,
0x3f800000,0x0,0x3f7b61fc,0xbe419b37,0x3f6db293,0xbebe1d4a,0x3f577026,0xbf0a48ad,0x3f396842,0xbf3085bb,0x3f14b039,0xbf5064af,0x3ed53641,0xbf68bf3c,0x3e72b651,0xbf78b47b,
0x3f800000,0x0,0x3f800000,0x0,0x3f800000,0x0,0x3f800000,0x0,0x3f800000,0x0,0x3f800000,0x0,0x3f800000,0x0,0x3f800000,0x0,
0x3f7b14be,0xbe47c5c2,0x3f79c79d,0xbe605c13,0x3f7853f8,0xbe78cfcc,0x3f76ba07,0xbe888e93,0x3f74fa0b,0xbe94a031,0x3f731447,0xbea09ae5,0x3f710908,0xbeac7cd4,0x3f6ed89e,0xbeb8442a,
0x3f7fb10f,0xbd48fb30,0x3f7f9c18,0xbd621469,0x3f7f84ab,0xbd7b2b74,0x3f7f6ac7,0xbd8a200a,0x3f7f4e6d,0xbd96a905,0x3f7f2f9d,0xbda3308c,0x3f7f0e58,0xbdafb680,0x3f7eea9d,0xbdbc3ac3,
0x3f7853f8,0xbe78cfcc,0x3f764d97,0xbe8b9507,0x3f740bdd,0xbe9aa086,0x3f718f57,0xbea986c4,0x3f6ed89e,0xbeb8442a,0x3f6be858,0xbec6d529,0x3f68bf3c,0xbed53641,0x3f655e0b,0xbee363fa,
0x3f7ec46d,0xbdc8bd36,0x3f7e70b0,0xbde1bc2e,0x3f7e1324,0xbdfab273,0x3f7dabcc,0xbe09cf86,0x3f7d3aac,0xbe164083,0x3f7cbfc9,0xbe22abb6,0x3f7c3b28,0xbe2f10a2,0x3f7baccd,0xbe3b6ecf,
0x3f74fa0b,0xbe94a031,0x3f721352,0xbea68f12,0x3f6ed89e,0xbeb8442a,0x3f6b4b0c,0xbec9b953,0x3f676bd8,0xbedae880,0x3f633c5a,0xbeebcbbb,0x3f5ebe05,0xbefc5d27,0x3f59f26a,0xbf064b82,
0x3f7d3aac,0xbe164083,0x3f7c7eb0,0xbe28defc,0x3f7baccd,0xbe3b6ecf,0x3f7ac516,0xbe4dee60,0x3f79c79d,0xbe605c13,0x3f78b47b,0xbe72b651,0x3f778bc5,0xbe827dc0,0x3f764d97,0xbe8b9507,
0x3f710908,0xbeac7cd4,0x3f6d1c1d,0xbec1071e,0x3f68bf3c,0xbed53641,0x3f63f473,0xbee900b7,0x3f5ebe05,0xbefc5d27,0x3f591e6a,0xbf07a136,0x3f531849,0xbf10d3cd,0x3f4cae79,0xbf19c200,
0x3f6c835e,0xbec3ef15,0x3f676bd8,0xbedae880,0x3f61c598,0xbef15aea,0x3f5b941a,0xbf039c3d,0x3f54db31,0xbf0e39da,0x3f4d9f02,0xbf187fc0,0x3f45e403,0xbf226799,0x3f3daef9,0xbf2beb4a,
0x3f54db31,0xbf0e39da,0x3f49d112,0xbf1d7fd1,0x3f3daef9,0xbf2beb4a,0x3f3085bb,0xbf396842,0x3f226799,0xbf45e403,0x3f13682a,0xbf514d3d,0x3f039c3d,0xbf5b941a,0x3ee63375,0xbf64aa59,
0x3f676bd8,0xbedae880,0x3f6106f2,0xbef41f07,0x3f59f26a,0xbf064b82,0x3f5233c6,0xbf121eb0,0x3f49d112,0xbf1d7fd1,0x3f40d0da,0xbf286605,0x3f373a23,0xbf32c8c9,0x3f2d1469,0xbf3ca003,
0x3f4d9f02,0xbf187fc0,0x3f40d0da,0xbf286605,0x3f32c8c9,0xbf373a23,0x3f239da9,0xbf44e3f5,0x3f13682a,0xbf514d3d,0x3f0242b1,0xbf5c61c7,0x3ee0924f,0xbf660f88,0x3ebb31a0,0xbf6e46be,
0x3f61c598,0xbef15aea,0x3f59f26a,0xbf064b82,0x3f514d3d,0xbf13682a,0x3f47de65,0xbf1ff6cb,0x3f3daef9,0xbf2beb4a,0x3f32c8c9,0xbf373a23,0x3f273656,0xbf41d870,0x3f1b02c6,0xbf4bbbf8,
0x3f45e403,0xbf226799,0x3f373a23,0xbf32c8c9,0x3f273656,0xbf41d870,0x3f15f6d9,0xbf4f7a1f,0x3f039c3d,0xbf5b941a,0x3ee0924f,0xbf660f88,0x3eb8442a,0xbf6ed89e,0x3e8e9a22,0xbf75dec6,
0x3f5b941a,0xbf039c3d,0x3f5233c6,0xbf121eb0,0x3f47de65,0xbf1ff6cb,0x3f3ca003,0xbf2d1469,0x3f3085bb,0xbf396842,0x3f239da9,0xbf44e3f5,0x3f15f6d9,0xbf4f7a1f,0x3f07a136,0xbf591e6a,
0x3f3daef9,0xbf2beb4a,0x3f2d1469,0xbf3ca003,0x3f1b02c6,0xbf4bbbf8,0x3f07a136,0xbf591e6a,0x3ee63375,0xbf64aa59,0x3ebb31a0,0xbf6e46be,0x3e8e9a22,0xbf75dec6,0x3e419b37,0xbf7b61fc,
0x3f3504f3,0xbf3504f3,0x3f226799,0xbf45e403,0x3f0e39da,0xbf54db31,0x3ef15aea,0xbf61c598,0x3ec3ef15,0xbf6c835e,0x3e94a031,0xbf74fa0b,0x3e47c5c2,0xbf7b14be,0x3dc8bd36,0xbf7ec46d,
0x3f0e39da,0xbf54db31,0x3ee63375,0xbf64aa59,0x3eac7cd4,0xbf710908,0x3e605c13,0xbf79c79d,0x3dc8bd36,0xbf7ec46d,0xbcc90ab0,0xbf7fec43,0xbe164083,0xbf7d3aac,0xbe888e93,0xbf76ba07,
0x3f2beb4a,0xbf3daef9,0x3f173c07,0xbf4e8d90,0x3f00e7e4,0xbf5d2d53,0x3ed25a09,0xbf696591,0x3ea09ae5,0xbf731447,0x3e5a3997,0xbf7a1e84,0x3de1bc2e,0xbf7e70b0,0x3bc90f88,0xbf7ffec4,
0x3f039c3d,0xbf5b941a,0x3ecc9b8b,0xbf6aab7b,0x3e8e9a22,0xbf75dec6,0x3e1c76de,0xbf7cfe73,0x3cc90ab0,0xbf7fec43,0xbdd53db9,0xbf7e9bc9,0xbe6c9a7f,0xbf791298,0xbeb554ec,0xbf6f6830,
0x3f226799,0xbf45e403,0x3f0b9a6b,0xbf5695e5,0x3ee63375,0xbf64aa59,0x3eb263ef,0xbf6ff573,0x3e78cfcc,0xbf7853f8,0x3e09cf86,0xbf7dabcc,0x3cc90ab0,0xbf7fec43,0xbdafb680,0xbf7f0e58,
0x3ef15aea,0xbf61c598,0x3eb263ef,0xbf6ff573,0x3e605c13,0xbf79c79d,0x3dafb680,0xbf7f0e58,0xbd48fb30,0xbf7fb10f,0xbe3b6ecf,0xbf7baccd,0xbea09ae5,0xbf731447,0xbee0924f,0xbf660f88,
0x3f187fc0,0xbf4d9f02,0x3eff17b2,0xbf5df6be,0x3ec9b953,0xbf6b4b0c,0x3e919ddd,0xbf756d97,0x3e2f10a2,0xbf7c3b28,0x3d621469,0xbf7f9c18,0xbd7b2b74,0xbf7f84ab,0xbe354098,0xbf7bf531,
0x3edae880,0xbf676bd8,0x3e97a117,0xbf748422,0x3e22abb6,0xbf7cbfc9,0x3c96c9b6,0xbf7ff4e6,0xbdfab273,0xbf7e1324,0xbe8586ce,0xbf772417,0xbec9b953,0xbf6b4b0c,0xbf04f484,0xbf5ac450,
0x3ec3ef15,0xbf6c835e,0x3e78cfcc,0xbf7853f8,0x3dc8bd36,0xbf7ec46d,0xbd48fb30,0xbf7fb10f,0xbe47c5c2,0xbf7b14be,0xbeac7cd4,0xbf710908,0xbef15aea,0xbf61c598,0xbf187fc0,0xbf4d9f02,
0x3e47c5c2,0xbf7b14be,0x3cc90ab0,0xbf7fec43,0xbe164083,0xbf7d3aac,0xbea09ae5,0xbf731447,0xbef15aea,0xbf61c598,0xbf1d7fd1,0xbf49d112,0xbf3daef9,0xbf2beb4a,0xbf584853,0xbf08f59b,
0x3eac7cd4,0xbf710908,0x3e419b37,0xbf7b61fc,0x3d16c32c,0xbf7fd397,0xbdee3876,0xbf7e4323,0xbe888e93,0xbf76ba07,0xbed25a09,0xbf696591,0xbf0b9a6b,0xbf5695e5,0xbf2ac082,0xbf3ebc1b,
0x3e164083,0xbf7d3aac,0xbcfb49ba,0xbf7fe129,0xbe541501,0xbf7a7302,0xbec1071e,0xbf6d1c1d,0xbf08f59b,0xbf584853,0xbf2d1469,0xbf3ca003,0xbf4bbbf8,0xbf1b02c6,0xbf63f473,0xbee900b7,
0x3e94a031,0xbf74fa0b,0x3e09cf86,0xbf7dabcc,0xbcc90ab0,0xbf7fec43,0xbe3b6ecf,0xbf7baccd,0xbeac7cd4,0xbf710908,0xbef6e0cb,0xbf604621,0xbf1d7fd1,0xbf49d112,0xbf3b8f3b,0xbf2e3bde,
0x3dc8bd36,0xbf7ec46d,0xbdafb680,0xbf7f0e58,0xbe888e93,0xbf76ba07,0xbee0924f,0xbf660f88,0xbf187fc0,0xbf4d9f02,0xbf3b8f3b,0xbf2e3bde,0xbf584853,0xbf08f59b,0xbf6db293,0xbebe1d4a,
0x3e78cfcc,0xbf7853f8,0x3da3308c,0xbf7f2f9d,0xbdafb680,0xbf7f0e58,0xbe7ee6e1,0xbf77f110,0xbecf7bca,0xbf6a09a7,0xbf0cead0,0xbf55b993,0xbf2e3bde,0xbf3b8f3b,0xbf4ac77f,0xbf1c420c,
0x3d48fb30,0xbf7fb10f,0xbe1008b7,0xbf7d7474,0xbea68f12,0xbf721352,0xbeff17b2,0xbf5df6be,0xbf273656,0xbf41d870,0xbf48d8b3,0xbf1ebc12,0xbf633c5a,0xbeebcbbb,0xbf756d97,0xbe919ddd,
0x3f800000,0x0,0x3f800000,0x0,0x3f800000,0x0,0x3f800000,0x0,0x3f800000,0x0,0x3f800000,0x0,0x3f800000,0x0,0x3f800000,0x0,
0x3f6c835e,0xbec3ef15,0x3f6a09a7,0xbecf7bca,0x3f676bd8,0xbedae880,0x3f64aa59,0xbee63375,0x3f61c598,0xbef15aea,0x3f5ebe05,0xbefc5d27,0x3f5b941a,0xbf039c3d,0x3f584853,0xbf08f59b,
0x3f7ec46d,0xbdc8bd36,0x3f7e9bc9,0xbdd53db9,0x3f7e70b0,0xbde1bc2e,0x3f7e4323,0xbdee3876,0x3f7e1324,0xbdfab273,0x3f7de0b1,0xbe039502,0x3f7dabcc,0xbe09cf86,0x3f7d7474,0xbe1008b7,
0x3f61c598,0xbef15aea,0x3f5df6be,0xbeff17b2,0x3f59f26a,0xbf064b82,0x3f55b993,0xbf0cead0,0x3f514d3d,0xbf13682a,0x3f4cae79,0xbf19c200,0x3f47de65,0xbf1ff6cb,0x3f42de29,0xbf26050a,
0x3f7b14be,0xbe47c5c2,0x3f7a7302,0xbe541501,0x3f79c79d,0xbe605c13,0x3f791298,0xbe6c9a7f,0x3f7853f8,0xbe78cfcc,0x3f778bc5,0xbe827dc0,0x3f76ba07,0xbe888e93,0x3f75dec6,0xbe8e9a22,
0x3f54db31,0xbf0e39da,0x3f4f7a1f,0xbf15f6d9,0x3f49d112,0xbf1d7fd1,0x3f43e200,0xbf24d225,0x3f3daef9,0xbf2beb4a,0x3f373a23,0xbf32c8c9,0x3f3085bb,0xbf396842,0x3f299415,0xbf3fc767,
0x3f74fa0b,0xbe94a031,0x3f73913f,0xbe9d9e78,0x3f721352,0xbea68f12,0x3f708066,0xbeaf713a,0x3f6ed89e,0xbeb8442a,0x3f6d1c1d,0xbec1071e,0x3f6b4b0c,0xbec9b953,0x3f696591,0xbed25a09,
0x3f45e403,0xbf226799,0x3f3ebc1b,0xbf2ac082,0x3f373a23,0xbf32c8c9,0x3f2f61a5,0xbf3a7ca4,0x3f273656,0xbf41d870,0x3f1ebc12,0xbf48d8b3,0x3f15f6d9,0xbf4f7a1f,0x3f0cead0,0xbf55b993,
0x3f3504f3,0xbf3504f3,0x3f2beb4a,0xbf3daef9,0x3f226799,0xbf45e403,0x3f187fc0,0xbf4d9f02,0x3f0e39da,0xbf54db31,0x3f039c3d,0xbf5b941a,0x3ef15aea,0xbf61c598,0x3edae880,0xbf676bd8,
0x3ec3ef15,0xbf6c835e,0x3ea09ae5,0xbf731447,0x3e78cfcc,0xbf7853f8,0x3e2f10a2,0xbf7c3b28,0x3dc8bd36,0xbf7ec46d,0x3cc90ab0,0xbf7fec43,0xbd48fb30,0xbf7fb10f,0xbdfab273,0xbf7e1324,
0x3f226799,0xbf45e403,0x3f173c07,0xbf4e8d90,0x3f0b9a6b,0xbf5695e5,0x3eff17b2,0xbf5df6be,0x3ee63375,0xbf64aa59,0x3ecc9b8b,0xbf6aab7b,0x3eb263ef,0xbf6ff573,0x3e97a117,0xbf748422,
0x3e94a031,0xbf74fa0b,0x3e5a3997,0xbf7a1e84,0x3e09cf86,0xbf7dabcc,0x3d621469,0xbf7f9c18,0xbcc90ab0,0xbf7fec43,0xbdd53db9,0xbf7e9bc9,0xbe3b6ecf,0xbf7baccd,0xbe8586ce,0xbf772417,
0x3f0e39da,0xbf54db31,0x3f00e7e4,0xbf5d2d53,0x3ee63375,0xbf64aa59,0x3ec9b953,0xbf6b4b0c,0x3eac7cd4,0xbf710908,0x3e8e9a22,0xbf75dec6,0x3e605c13,0xbf79c79d,0x3e22abb6,0xbf7cbfc9,
0x3e47c5c2,0xbf7b14be,0x3de1bc2e,0xbf7e70b0,0x3cc90ab0,0xbf7fec43,0xbd7b2b74,0xbf7f84ab,0xbe164083,0xbf7d3aac,0xbe6c9a7f,0xbf791298,0xbea09ae5,0xbf731447,0xbec9b953,0xbf6b4b0c,
0x3ef15aea,0xbf61c598,0x3ed25a09,0xbf696591,0x3eb263ef,0xbf6ff573,0x3e919ddd,0xbf756d97,0x3e605c13,0xbf79c79d,0x3e1c76de,0xbf7cfe73,0x3dafb680,0xbf7f0e58,0x3c96c9b6,0xbf7ff4e6,
0x3dc8bd36,0xbf7ec46d,0x3bc90f88,0xbf7ffec4,0xbdafb680,0xbf7f0e58,0xbe354098,0xbf7bf531,0xbe888e93,0xbf76ba07,0xbeb554ec,0xbf6f6830,0xbee0924f,0xbf660f88,0xbf04f484,0xbf5ac450,
0x0,0xbf800000,0xbdc8bd36,0xbf7ec46d,0xbe47c5c2,0xbf7b14be,0xbe94a031,0xbf74fa0b,0xbec3ef15,0xbf6c835e,0xbef15aea,0xbf61c598,0xbf0e39da,0xbf54db31,0xbf226799,0xbf45e403,
0xbec3ef15,0xbf6c835e,0xbefc5d27,0xbf5ebe05,0xbf187fc0,0xbf4d9f02,0xbf3085bb,0xbf396842,0xbf45e403,0xbf226799,0xbf584853,0xbf08f59b,0xbf676bd8,0xbedae880,0xbf731447,0xbea09ae5,
0xbdc8bd36,0xbf7ec46d,0xbe4dee60,0xbf7ac516,0xbe9aa086,0xbf740bdd,0xbecc9b8b,0xbf6aab7b,0xbefc5d27,0xbf5ebe05,0xbf14b039,0xbf5064af,0xbf299415,0xbf3fc767,0xbf3ca003,0xbf2d1469,
0xbef15aea,0xbf61c598,0xbf14b039,0xbf5064af,0xbf2e3bde,0xbf3b8f3b,0xbf44e3f5,0xbf239da9,0xbf584853,0xbf08f59b,0xbf6816a8,0xbed8106b,0xbf740bdd,0xbe9aa086,0xbf7bf531,0xbe354098,
0xbe47c5c2,0xbf7b14be,0xbe9aa086,0xbf740bdd,0xbecf7bca,0xbf6a09a7,0xbf00e7e4,0xbf5d2d53,0xbf187fc0,0xbf4d9f02,0xbf2e3bde,0xbf3b8f3b,0xbf41d870,0xbf273656,0xbf531849,0xbf10d3cd,
0xbf0e39da,0xbf54db31,0xbf299415,0xbf3fc767,0xbf41d870,0xbf273656,0xbf5695e5,0xbf0b9a6b,0xbf676bd8,0xbedae880,0xbf740bdd,0xbe9aa086,0xbf7c3b28,0xbe2f10a2,0xbf7fd397,0xbd16c32c,
0xbe94a031,0xbf74fa0b,0xbecc9b8b,0xbf6aab7b,0xbf00e7e4,0xbf5d2d53,0xbf19c200,0xbf4cae79,0xbf3085bb,0xbf396842,0xbf44e3f5,0xbf239da9,0xbf5695e5,0xbf0b9a6b,0xbf655e0b,0xbee363fa,
0xbf226799,0xbf45e403,0xbf3ca003,0xbf2d1469,0xbf531849,0xbf10d3cd,0xbf655e0b,0xbee363fa,0xbf731447,0xbea09ae5,0xbf7bf531,0xbe354098,0xbf7fd397,0xbd16c32c,0xbf7e9bc9,0x3dd53db9,
0xbf3504f3,0xbf3504f3,0xbf4d9f02,0xbf187fc0,0xbf61c598,0xbef15aea,0xbf710908,0xbeac7cd4,0xbf7b14be,0xbe47c5c2,0xbf7fb10f,0xbd48fb30,0xbf7ec46d,0x3dc8bd36,0xbf7853f8,0x3e78cfcc,
0xbf6c835e,0xbec3ef15,0xbf79c79d,0xbe605c13,0xbf7fb10f,0xbd48fb30,0xbf7e1324,0x3dfab273,0xbf74fa0b,0x3e94a031,0xbf64aa59,0x3ee63375,0xbf4d9f02,0x3f187fc0,0xbf3085bb,0x3f396842,
0xbf45e403,0xbf226799,0xbf5c61c7,0xbf0242b1,0xbf6db293,0xbebe1d4a,0xbf796e4e,0xbe667c66,0xbf7f4e6d,0xbd96a905,0xbf7f2f9d,0x3da3308c,0xbf791298,0x3e6c9a7f,0xbf6d1c1d,0x3ec1071e,
0xbf74fa0b,0xbe94a031,0xbf7e4323,0xbdee3876,0xbf7f84ab,0x3d7b2b74,0xbf78b47b,0x3e72b651,0xbf6a09a7,0x3ecf7bca,0xbf53fac3,0x3f0f8784,0xbf373a23,0x3f32c8c9,0xbf14b039,0x3f5064af,
0xbf54db31,0xbf0e39da,0xbf68bf3c,0xbed53641,0xbf76ba07,0xbe888e93,0xbf7e70b0,0xbde1bc2e,0xbf7fb10f,0x3d48fb30,0xbf7a7302,0x3e541501,0xbf6ed89e,0x3eb8442a,0xbf5d2d53,0x3f00e7e4,
0xbf7b14be,0xbe47c5c2,0xbf7ffb11,0xbc490e90,0xbf7c3b28,0x3e2f10a2,0xbf6ff573,0x3eb263ef,0xbf5b941a,0x3f039c3d,0xbf3fc767,0x3f299415,0xbf1d7fd1,0x3f49d112,0xbeebcbbb,0x3f633c5a,
0xbf61c598,0xbef15aea,0xbf7294f8,0xbea395c5,0xbf7cbfc9,0xbe22abb6,0xbf7ffec4,0x3bc90f88,0xbf7c3b28,0x3e2f10a2,0xbf718f57,0x3ea986c4,0xbf604621,0x3ef6e0cb,0xbf48d8b3,0x3f1ebc12,
0xbf7ec46d,0xbdc8bd36,0xbf7eea9d,0x3dbc3ac3,0xbf75dec6,0x3e8e9a22,0xbf63f473,0x3ee900b7,0xbf49d112,0x3f1d7fd1,0xbf286605,0x3f40d0da,0xbf00e7e4,0x3f5d2d53,0xbea986c4,0x3f718f57,
0x3f800000,0x0,0x3f800000,0x0,0x3f800000,0x0,0x3f800000,0x0,0x3f800000,0x0,0x3f800000,0x0,0x3f800000,0x0,0x3f800000,0x0,
0x3f54db31,0xbf0e39da,0x3f514d3d,0xbf13682a,0x3f4d9f02,0xbf187fc0,0x3f49d112,0xbf1d7fd1,0x3f45e403,0xbf226799,0x3f41d870,0xbf273656,0x3f3daef9,0xbf2beb4a,0x3f396842,0xbf3085bb,
0x3f7d3aac,0xbe164083,0x3f7cfe73,0xbe1c76de,0x3f7cbfc9,0xbe22abb6,0x3f7c7eb0,0xbe28defc,0x3f7c3b28,0xbe2f10a2,0x3f7bf531,0xbe354098,0x3f7baccd,0xbe3b6ecf,0x3f7b61fc,0xbe419b37,
0x3f3daef9,0xbf2beb4a,0x3f385216,0xbf31a81d,0x3f32c8c9,0xbf373a23,0x3f2d1469,0xbf3ca003,0x3f273656,0xbf41d870,0x3f212ff9,0xbf46e22a,0x3f1b02c6,0xbf4bbbf8,0x3f14b039,0xbf5064af,
0x3f74fa0b,0xbe94a031,0x3f740bdd,0xbe9aa086,0x3f731447,0xbea09ae5,0x3f721352,0xbea68f12,0x3f710908,0xbeac7cd4,0x3f6ff573,0xbeb263ef,0x3f6ed89e,0xbeb8442a,0x3f6db293,0xbebe1d4a,
0x3f226799,0xbf45e403,0x3f1b02c6,0xbf4bbbf8,0x3f13682a,0xbf514d3d,0x3f0b9a6b,0xbf5695e5,0x3f039c3d,0xbf5b941a,0x3ef6e0cb,0xbf604621,0x3ee63375,0xbf64aa59,0x3ed53641,0xbf68bf3c,
0x3f676bd8,0xbedae880,0x3f655e0b,0xbee363fa,0x3f633c5a,0xbeebcbbb,0x3f6106f2,0xbef41f07,0x3f5ebe05,0xbefc5d27,0x3f5c61c7,0xbf0242b1,0x3f59f26a,0xbf064b82,0x3f577026,0xbf0a48ad,
0x3f039c3d,0xbf5b941a,0x3ef41f07,0xbf6106f2,0x3ee0924f,0xbf660f88,0x3ecc9b8b,0xbf6aab7b,0x3eb8442a,0xbf6ed89e,0x3ea395c5,0xbf7294f8,0x3e8e9a22,0xbf75dec6,0x3e72b651,0xbf78b47b,
0x3ec3ef15,0xbf6c835e,0x3eac7cd4,0xbf710908,0x3e94a031,0xbf74fa0b,0x3e78cfcc,0xbf7853f8,0x3e47c5c2,0xbf7b14be,0x3e164083,0xbf7d3aac,0x3dc8bd36,0xbf7ec46d,0x3d48fb30,0xbf7fb10f,
0xbe47c5c2,0xbf7b14be,0xbe888e93,0xbf76ba07,0xbeac7cd4,0xbf710908,0xbecf7bca,0xbf6a09a7,0xbef15aea,0xbf61c598,0xbf08f59b,0xbf584853,0xbf187fc0,0xbf4d9f02,0xbf273656,0xbf41d870,
0x3e78cfcc,0xbf7853f8,0x3e419b37,0xbf7b61fc,0x3e09cf86,0xbf7dabcc,0x3da3308c,0xbf7f2f9d,0x3cc90ab0,0xbf7fec43,0xbcfb49ba,0xbf7fe129,0xbdafb680,0xbf7f0e58,0xbe1008b7,0xbf7d7474,
0xbeac7cd4,0xbf710908,0xbed25a09,0xbf696591,0xbef6e0cb,0xbf604621,0xbf0cead0,0xbf55b993,0xbf1d7fd1,0xbf49d112,0xbf2d1469,0xbf3ca003,0xbf3b8f3b,0xbf2e3bde,0xbf48d8b3,0xbf1ebc12,
0x3dc8bd36,0xbf7ec46d,0x3d16c32c,0xbf7fd397,0xbcc90ab0,0xbf7fec43,0xbdafb680,0xbf7f0e58,0xbe164083,0xbf7d3aac,0xbe541501,0xbf7a7302,0xbe888e93,0xbf76ba07,0xbea68f12,0xbf721352,
0xbef15aea,0xbf61c598,0xbf0b9a6b,0xbf5695e5,0xbf1d7fd1,0xbf49d112,0xbf2e3bde,0xbf3b8f3b,0xbf3daef9,0xbf2beb4a,0xbf4bbbf8,0xbf1b02c6,0xbf584853,0xbf08f59b,0xbf633c5a,0xbeebcbbb,
0xbd48fb30,0xbf7fb10f,0xbdee3876,0xbf7e4323,0xbe3b6ecf,0xbf7baccd,0xbe7ee6e1,0xbf77f110,0xbea09ae5,0xbf731447,0xbec1071e,0xbf6d1c1d,0xbee0924f,0xbf660f88,0xbeff17b2,0xbf5df6be,
0xbf187fc0,0xbf4d9f02,0xbf2ac082,0xbf3ebc1b,0xbf3b8f3b,0xbf2e3bde,0xbf4ac77f,0xbf1c420c,0xbf584853,0xbf08f59b,0xbf63f473,0xbee900b7,0xbf6db293,0xbebe1d4a,0xbf756d97,0xbe919ddd,
0xbf3504f3,0xbf3504f3,0xbf45e403,0xbf226799,0xbf54db31,0xbf0e39da,0xbf61c598,0xbef15aea,0xbf6c835e,0xbec3ef15,0xbf74fa0b,0xbe94a031,0xbf7b14be,0xbe47c5c2,0xbf7ec46d,0xbdc8bd36,
0xbf7b14be,0xbe47c5c2,0xbf7f4e6d,0xbd96a905,0xbf7fb10f,0x3d48fb30,0xbf7c3b28,0x3e2f10a2,0xbf74fa0b,0x3e94a031,0xbf6a09a7,0x3ecf7bca,0xbf5b941a,0x3f039c3d,0xbf49d112,0x3f1d7fd1,
0xbf4d9f02,0xbf187fc0,0xbf5c61c7,0xbf0242b1,0xbf68bf3c,0xbed53641,0xbf7294f8,0xbea395c5,0xbf79c79d,0xbe605c13,0xbf7e4323,0xbdee3876,0xbf7ffb11,0xbc490e90,0xbf7eea9d,0x3dbc3ac3,
0xbf7fb10f,0xbd48fb30,0xbf7f2f9d,0x3da3308c,0xbf7a7302,0x3e541501,0xbf718f57,0x3ea986c4,0xbf64aa59,0x3ee63375,0xbf53fac3,0x3f0f8784,0xbf3fc767,0x3f299415,0xbf286605,0x3f40d0da,
0xbf61c598,0xbef15aea,0xbf6db293,0xbebe1d4a,0xbf76ba07,0xbe888e93,0xbf7cbfc9,0xbe22abb6,0xbf7fb10f,0xbd48fb30,0xbf7f84ab,0x3d7b2b74,0xbf7c3b28,0x3e2f10a2,0xbf75dec6,0x3e8e9a22,
0xbf7ec46d,0x3dc8bd36,0xbf791298,0x3e6c9a7f,0xbf6ed89e,0x3eb8442a,0xbf604621,0x3ef6e0cb,0xbf4d9f02,0x3f187fc0,0xbf373a23,0x3f32c8c9,0xbf1d7fd1,0x3f49d112,0xbf00e7e4,0x3f5d2d53,
0xbf710908,0xbeac7cd4,0xbf796e4e,0xbe667c66,0xbf7e70b0,0xbde1bc2e,0xbf7ffec4,0x3bc90f88,0xbf7e1324,0x3dfab273,0xbf78b47b,0x3e72b651,0xbf6ff573,0x3eb263ef,0xbf63f473,0x3ee900b7,
0xbf7853f8,0x3e78cfcc,0xbf6d1c1d,0x3ec1071e,0xbf5d2d53,0x3f00e7e4,0xbf48d8b3,0x3f1ebc12,0xbf3085bb,0x3f396842,0xbf14b039,0x3f5064af,0xbeebcbbb,0x3f633c5a,0xbea986c4,0x3f718f57,
0xbf6c835e,0x3ec3ef15,0xbf5b941a,0x3f039c3d,0xbf45e403,0x3f226799,0xbf2beb4a,0x3f3daef9,0xbf0e39da,0x3f54db31,0xbedae880,0x3f676bd8,0xbe94a031,0x3f74fa0b,0xbe164083,0x3f7d3aac,
0xbf0e39da,0x3f54db31,0xbecf7bca,0x3f6a09a7,0xbe78cfcc,0x3f7853f8,0xbd96a905,0x3f7f4e6d,0x3dc8bd36,0x3f7ec46d,0x3e888e93,0x3f76ba07,0x3edae880,0x3f676bd8,0x3f13682a,0x3f514d3d,
0xbf5b941a,0x3f039c3d,0xbf44e3f5,0x3f239da9,0xbf299415,0x3f3fc767,0xbf0a48ad,0x3f577026,0xbecf7bca,0x3f6a09a7,0xbe8586ce,0x3f772417,0xbde1bc2e,0x3f7e70b0,0x3d2fe007,0x3f7fc38f,
0xbedae880,0x3f676bd8,0xbe8586ce,0x3f772417,0xbdafb680,0x3f7f0e58,0x3dbc3ac3,0x3f7eea9d,0x3e888e93,0x3f76ba07,0x3eddbe79,0x3f66becc,0x3f15f6d9,0x3f4f7a1f,0x3f385216,0x3f31a81d,
0xbf45e403,0x3f226799,0xbf299415,0x3f3fc767,0xbf08f59b,0x3f584853,0xbec9b953,0x3f6b4b0c,0xbe78cfcc,0x3f7853f8,0xbdafb680,0x3f7f0e58,0x3d96a905,0x3f7f4e6d,0x3e6c9a7f,0x3f791298,
0xbe94a031,0x3f74fa0b,0xbde1bc2e,0x3f7e70b0,0x3d96a905,0x3f7f4e6d,0x3e827dc0,0x3f778bc5,0x3edae880,0x3f676bd8,0x3f15f6d9,0x3f4f7a1f,0x3f396842,0x3f3085bb,0x3f5695e5,0x3f0b9a6b,
0xbf2beb4a,0x3f3daef9,0xbf0a48ad,0x3f577026,0xbec9b953,0x3f6b4b0c,0xbe72b651,0x3f78b47b,0xbd96a905,0x3f7f4e6d,0x3dbc3ac3,0x3f7eea9d,0x3e827dc0,0x3f778bc5,0x3ed25a09,0x3f696591,
0xbe164083,0x3f7d3aac,0x3d2fe007,0x3f7fc38f,0x3e6c9a7f,0x3f791298,0x3ed25a09,0x3f696591,0x3f13682a,0x3f514d3d,0x3f385216,0x3f31a81d,0x3f5695e5,0x3f0b9a6b,0x3f6d1c1d,0x3ec1071e,
0x3e00,0x3e00,0x3e00,0x3e00,0x3e00,0x3e00,0x3e00,0x3e00,0x3e00,0x3e00,0x3e00,0x3e00,0x3e00,0x3e00,0x3e00,0x3e00,
0xbd443ded,0xbcc83dfb,0xbc493dff,0xbd153df5,0xbdb53db5,0xbdd53d8e,0xbdc63da2,0xbde23d71,0xbe000000,0xbdfbbcc8,0xbdffbc49,0xbdf5bd15,0xbdb5bdb5,0xbd8ebdd5,0xbda2bdc6,0xbd71bde2,
0xbdb53db5,0xbd443ded,0xbcc83dfb,0xbd8e3dd5,0xbe000000,0xbdedbd44,0xbdfbbcc8,0xbdd5bd8e,0xbe00,0x3d44bded,0x3cc8bdfb,0x3d8ebdd5,0x3e000000,0x3ded3d44,0x3dfb3cc8,0x3dd53d8e,
0xbded3d44,0xbd8e3dd5,0xbd153df5,0xbdc63da2,0xbdb5bdb5,0xbcc8bdfb,0xbd71bde2,0x3c49bdff,0x3e000000,0x3dd53d8e,0x3df53d15,0x3da23dc6,0xbdb53db5,0xbdfb3cc8,0xbde23d71,0xbdffbc49,
0xbe000000,0xbdb53db5,0xbd443ded,0xbded3d44,0xbe00,0x3db5bdb5,0x3d44bded,0x3dedbd44,0x3e00,0xbdb53db5,0xbd443ded,0xbded3d44,0xbe00,0x3db5bdb5,0x3d44bded,0x3dedbd44,
0xbdedbd44,0xbdd53d8e,0xbd713de2,0xbdff3c49,0x3db5bdb5,0x3dfb3cc8,0x3df5bd15,0x3dc63da2,0xbe000000,0xbd8ebdd5,0xbde2bd71,0xbc49bdff,0x3db53db5,0xbcc83dfb,0x3d153df5,0xbda23dc6,
0xbdb5bdb5,0xbded3d44,0xbd8e3dd5,0xbdfbbcc8,0x3e000000,0x3d443ded,0x3dd53d8e,0xbcc83dfb,0xbe00,0x3dedbd44,0x3d8ebdd5,0x3dfb3cc8,0xbe000000,0xbd44bded,0xbdd5bd8e,0x3cc8bdfb,
0xbd44bded,0xbdfb3cc8,0xbda23dc6,0xbde2bd71,0x3db53db5,0xbd8e3dd5,0x3c493dff,0xbdf53d15,0x3e000000,0x3cc83dfb,0x3dc63da2,0xbd713de2,0x3db5bdb5,0x3dd53d8e,0x3dffbc49,0x3d153df5,
0xbe00,0xbe000000,0xbdb53db5,0xbdb5bdb5,0x3e00,0xbe000000,0xbdb53db5,0xbdb5bdb5,0x3e00,0xbe000000,0xbdb53db5,0xbdb5bdb5,0x3e00,0xbe000000,0xbdb53db5,0xbdb5bdb5,
0x3d44bded,0xbdfbbcc8,0xbdc63da2,0xbd71bde2,0xbdb53db5,0xbd8ebdd5,0xbdffbc49,0x3d15bdf5,0xbe000000,0x3cc8bdfb,0xbda2bdc6,0x3de2bd71,0xbdb5bdb5,0x3dd5bd8e,0x3c49bdff,0x3df53d15,
0x3db5bdb5,0xbdedbd44,0xbdd53d8e,0xbcc8bdfb,0xbe000000,0x3d44bded,0xbd8ebdd5,0x3dfbbcc8,0xbe00,0x3ded3d44,0x3dd5bd8e,0x3cc83dfb,0x3e000000,0xbd443ded,0x3d8e3dd5,0xbdfb3cc8,
0x3dedbd44,0xbdd5bd8e,0xbde23d71,0x3c49bdff,0xbdb5bdb5,0x3dfbbcc8,0x3d15bdf5,0x3da23dc6,0x3e000000,0xbd8e3dd5,0x3d713de2,0xbdffbc49,0xbdb53db5,0xbcc8bdfb,0xbdf5bd15,0x3dc6bda2,
0x3e000000,0xbdb5bdb5,0xbded3d44,0x3d44bded,0xbe00,0x3db53db5,0x3dedbd44,0xbd443ded,0x3e00,0xbdb5bdb5,0xbded3d44,0x3d44bded,0xbe00,0x3db53db5,0x3dedbd44,0xbd443ded,
0x3ded3d44,0xbd8ebdd5,0xbdf53d15,0x3da2bdc6,0x3db5bdb5,0xbcc83dfb,0x3de23d71,0xbdff3c49,0xbe000000,0x3dd5bd8e,0xbd15bdf5,0x3dc63da2,0x3db53db5,0xbdfbbcc8,0xbd713de2,0xbc49bdff,
0x3db53db5,0xbd44bded,0xbdfb3cc8,0x3dd5bd8e,0x3e000000,0xbded3d44,0x3cc83dfb,0xbd8ebdd5,0xbe00,0x3d443ded,0x3dfbbcc8,0xbdd53d8e,0xbe000000,0x3dedbd44,0xbcc8bdfb,0x3d8e3dd5,
0x3d443ded,0xbcc8bdfb,0xbdff3c49,0x3df5bd15,0x3db53db5,0xbdd5bd8e,0xbda23dc6,0x3d71bde2,0x3e000000,0xbdfb3cc8,0x3c493dff,0xbd15bdf5,0x3db5bdb5,0xbd8e3dd5,0x3dc63da2,0xbde2bd71,
0x3e00,0xbe00,0xbe000000,0x3e000000,0x3e00,0xbe00,0xbe000000,0x3e000000,0x3e00,0xbe00,0xbe000000,0x3e000000,0x3e00,0xbe00,0xbe000000,0x3e000000,
0xbd443ded,0x3cc8bdfb,0xbdffbc49,0x3df53d15,0xbdb53db5,0x3dd5bd8e,0xbda2bdc6,0x3d713de2,0xbe000000,0x3dfb3cc8,0x3c49bdff,0xbd153df5,0xbdb5bdb5,0x3d8e3dd5,0x3dc6bda2,0xbde23d71,
0xbdb53db5,0x3d44bded,0xbdfbbcc8,0x3dd53d8e,0xbe000000,0x3ded3d44,0x3cc8bdfb,0xbd8e3dd5,0xbe00,0xbd443ded,0x3dfb3cc8,0xbdd5bd8e,0x3e000000,0xbdedbd44,0xbcc83dfb,0x3d8ebdd5,
0xbded3d44,0x3d8ebdd5,0xbdf5bd15,0x3da23dc6,0xbdb5bdb5,0x3cc83dfb,0x3de2bd71,0xbdffbc49,0x3e000000,0xbdd5bd8e,0xbd153df5,0x3dc6bda2,0xbdb53db5,0x3dfbbcc8,0xbd71bde2,0xbc493dff,
0xbe000000,0x3db5bdb5,0xbdedbd44,0x3d443ded,0xbe00,0xbdb53db5,0x3ded3d44,0xbd44bded,0x3e00,0x3db5bdb5,0xbdedbd44,0x3d443ded,0xbe00,0xbdb53db5,0x3ded3d44,0xbd44bded,
0xbdedbd44,0x3dd5bd8e,0xbde2bd71,0x3c493dff,0x3db5bdb5,0xbdfbbcc8,0x3d153df5,0x3da2bdc6,0xbe000000,0x3d8e3dd5,0x3d71bde2,0xbdff3c49,0x3db53db5,0x3cc8bdfb,0xbdf53d15,0x3dc63da2,
0xbdb5bdb5,0x3dedbd44,0xbdd5bd8e,0xbcc83dfb,0x3e000000,0xbd44bded,0xbd8e3dd5,0x3dfb3cc8,0xbe00,0xbded3d44,0x3dd53d8e,0x3cc8bdfb,0xbe000000,0x3d443ded,0x3d8ebdd5,0xbdfbbcc8,
0xbd44bded,0x3dfbbcc8,0xbdc6bda2,0xbd713de2,0x3db53db5,0x3d8ebdd5,0xbdff3c49,0x3d153df5,0x3e000000,0xbcc8bdfb,0xbda23dc6,0x3de23d71,0x3db5bdb5,0xbdd5bd8e,0x3c493dff,0x3df5bd15,
0xbe00,0x3e000000,0xbdb5bdb5,0xbdb53db5,0x3e00,0x3e000000,0xbdb5bdb5,0xbdb53db5,0x3e00,0x3e000000,0xbdb5bdb5,0xbdb53db5,0x3e00,0x3e000000,0xbdb5bdb5,0xbdb53db5,
0x3d44bded,0x3dfb3cc8,0xbda2bdc6,0xbde23d71,0xbdb53db5,0x3d8e3dd5,0x3c49bdff,0xbdf5bd15,0xbe000000,0xbcc83dfb,0x3dc6bda2,0xbd71bde2,0xbdb5bdb5,0xbdd53d8e,0x3dff3c49,0x3d15bdf5,
0x3db5bdb5,0x3ded3d44,0xbd8ebdd5,0xbdfb3cc8,0xbe000000,0xbd443ded,0x3dd5bd8e,0xbcc8bdfb,0xbe00,0xbdedbd44,0x3d8e3dd5,0x3dfbbcc8,0x3e000000,0x3d44bded,0xbdd53d8e,0x3cc83dfb,
0x3dedbd44,0x3dd53d8e,0xbd71bde2,0xbdffbc49,0xbdb5bdb5,0xbdfb3cc8,0x3df53d15,0x3dc6bda2,0x3e000000,0x3d8ebdd5,0xbde23d71,0xbc493dff,0xbdb53db5,0x3cc83dfb,0x3d15bdf5,0xbda2bdc6,
0x3e000000,0x3db53db5,0xbd44bded,0xbdedbd44,0xbe00,0xbdb5bdb5,0x3d443ded,0x3ded3d44,0x3e00,0x3db53db5,0xbd44bded,0xbdedbd44,0xbe00,0xbdb5bdb5,0x3d443ded,0x3ded3d44,
0x3ded3d44,0x3d8e3dd5,0xbd15bdf5,0xbdc6bda2,0x3db5bdb5,0x3cc8bdfb,0xbd713de2,0x3c493dff,0xbe000000,0xbdd53d8e,0x3df5bd15,0x3da2bdc6,0x3db53db5,0x3dfb3cc8,0xbde2bd71,0xbdff3c49,
0x3db53db5,0x3d443ded,0xbcc8bdfb,0xbd8ebdd5,0x3e000000,0x3dedbd44,0xbdfb3cc8,0xbdd53d8e,0xbe00,0xbd44bded,0x3cc83dfb,0x3d8e3dd5,0xbe000000,0xbded3d44,0x3dfbbcc8,0x3dd5bd8e,
0x3d443ded,0x3cc83dfb,0xbc49bdff,0xbd15bdf5,0x3db53db5,0x3dd53d8e,0xbdc6bda2,0xbde2bd71,0x3e000000,0x3dfbbcc8,0xbdff3c49,0xbdf53d15,0x3db5bdb5,0x3d8ebdd5,0xbda23dc6,0xbd713de2,
0x3d803d80,0x3e00,0x3e00,0x3e00,0x3e00,0x3e00,0x3e00,0x3e00,0x3e00,0x3e00,0x3e00,0x3e00,0x3e00,0x3e00,0x3e00,0x3e00,
0xbd803d80,0x3cc8bdfb,0x3c49bdff,0x3d15bdf5,0xbded3d44,0x3dd5bd8e,0x3dc6bda2,0x3de2bd71,0xbdedbd44,0x3dfb3cc8,0x3dff3c49,0x3df53d15,0xbd44bded,0x3d8e3dd5,0x3da23dc6,0x3d713de2,
0x3d803d80,0xbd443ded,0xbcc83dfb,0xbd8e3dd5,0xbdb5bdb5,0xbdedbd44,0xbdfbbcc8,0xbdd5bd8e,0x3db5bdb5,0x3d44bded,0x3cc8bdfb,0x3d8ebdd5,0x3db53db5,0x3ded3d44,0x3dfb3cc8,0x3dd53d8e,
0xbd803d80,0x3d8ebdd5,0x3d15bdf5,0x3dc6bda2,0x3d44bded,0x3cc83dfb,0x3d713de2,0xbc493dff,0x3d443ded,0xbdd5bd8e,0xbdf5bd15,0xbda2bdc6,0xbdedbd44,0x3dfbbcc8,0x3de2bd71,0x3dff3c49,
0x3d803d80,0xbdb53db5,0xbd443ded,0xbded3d44,0x3e000000,0x3db5bdb5,0x3d44bded,0x3dedbd44,0xbe000000,0xbdb53db5,0xbd443ded,0xbded3d44,0x3e000000,0x3db5bdb5,0x3d44bded,0x3dedbd44,
0xbd803d80,0x3dd5bd8e,0x3d71bde2,0x3dffbc49,0x3d443ded,0xbdfbbcc8,0xbdf53d15,0xbdc6bda2,0x3d44bded,0x3d8e3dd5,0x3de23d71,0x3c493dff,0xbded3d44,0x3cc8bdfb,0xbd15bdf5,0x3da2bdc6,
0x3d803d80,0xbded3d44,0xbd8e3dd5,0xbdfbbcc8,0xbdb53db5,0x3d443ded,0x3dd53d8e,0xbcc83dfb,0x3db53db5,0x3dedbd44,0x3d8ebdd5,0x3dfb3cc8,0x3db5bdb5,0xbd44bded,0xbdd5bd8e,0x3cc8bdfb,
0xbd803d80,0x3dfbbcc8,0x3da2bdc6,0x3de23d71,0xbdedbd44,0x3d8ebdd5,0xbc49bdff,0x3df5bd15,0xbded3d44,0xbcc8bdfb,0xbdc6bda2,0x3d71bde2,0xbd443ded,0xbdd5bd8e,0xbdff3c49,0xbd15bdf5,
0x3d803d80,0xbe000000,0xbdb53db5,0xbdb5bdb5,0xbe00,0xbe000000,0xbdb53db5,0xbdb5bdb5,0xbe00,0xbe000000,0xbdb53db5,0xbdb5bdb5,0xbe00,0xbe000000,0xbdb53db5,0xbdb5bdb5,
0xbd803d80,0x3dfb3cc8,0x3dc6bda2,0x3d713de2,0x3dedbd44,0x3d8e3dd5,0x3dff3c49,0xbd153df5,0x3ded3d44,0xbcc83dfb,0x3da23dc6,0xbde23d71,0x3d443ded,0xbdd53d8e,0xbc493dff,0xbdf5bd15,
0x3d803d80,0xbdedbd44,0xbdd53d8e,0xbcc8bdfb,0x3db53db5,0x3d44bded,0xbd8ebdd5,0x3dfbbcc8,0xbdb53db5,0x3ded3d44,0x3dd5bd8e,0x3cc83dfb,0xbdb5bdb5,0xbd443ded,0x3d8e3dd5,0xbdfb3cc8,
0xbd803d80,0x3dd53d8e,0x3de2bd71,0xbc493dff,0xbd443ded,0xbdfb3cc8,0xbd153df5,0xbda2bdc6,0xbd44bded,0x3d8ebdd5,0xbd71bde2,0x3dff3c49,0x3ded3d44,0x3cc83dfb,0x3df53d15,0xbdc63da2,
0x3d803d80,0xbdb5bdb5,0xbded3d44,0x3d44bded,0xbe000000,0x3db53db5,0x3dedbd44,0xbd443ded,0x3e000000,0xbdb5bdb5,0xbded3d44,0x3d44bded,0xbe000000,0x3db53db5,0x3dedbd44,0xbd443ded,
0xbd803d80,0x3d8e3dd5,0x3df5bd15,0xbda23dc6,0xbd44bded,0x3cc8bdfb,0xbde2bd71,0x3dffbc49,0xbd443ded,0xbdd53d8e,0x3d153df5,0xbdc6bda2,0x3dedbd44,0x3dfb3cc8,0x3d71bde2,0x3c493dff,
0x3d803d80,0xbd44bded,0xbdfb3cc8,0x3dd5bd8e,0x3db5bdb5,0xbded3d44,0x3cc83dfb,0xbd8ebdd5,0xbdb5bdb5,0x3d443ded,0x3dfbbcc8,0xbdd53d8e,0xbdb53db5,0x3dedbd44,0xbcc8bdfb,0x3d8e3dd5,
0xbd803d80,0x3cc83dfb,0x3dffbc49,0xbdf53d15,0x3ded3d44,0x3dd53d8e,0x3da2bdc6,0xbd713de2,0x3dedbd44,0x3dfbbcc8,0xbc49bdff,0x3d153df5,0x3d44bded,0x3d8ebdd5,0xbdc6bda2,0x3de23d71,
0x3d803d80,0xbe00,0xbe000000,0x3e000000,0x3e00,0xbe00,0xbe000000,0x3e000000,0x3e00,0xbe00,0xbe000000,0x3e000000,0x3e00,0xbe00,0xbe000000,0x3e000000,
0xbd803d80,0xbcc83dfb,0x3dff3c49,0xbdf5bd15,0xbded3d44,0xbdd53d8e,0x3da23dc6,0xbd71bde2,0xbdedbd44,0xbdfbbcc8,0xbc493dff,0x3d15bdf5,0xbd44bded,0xbd8ebdd5,0xbdc63da2,0x3de2bd71,
0x3d803d80,0x3d44bded,0xbdfbbcc8,0x3dd53d8e,0xbdb5bdb5,0x3ded3d44,0x3cc8bdfb,0xbd8e3dd5,0x3db5bdb5,0xbd443ded,0x3dfb3cc8,0xbdd5bd8e,0x3db53db5,0xbdedbd44,0xbcc83dfb,0x3d8ebdd5,
0xbd803d80,0xbd8e3dd5,0x3df53d15,0xbda2bdc6,0x3d44bded,0xbcc8bdfb,0xbde23d71,0x3dff3c49,0x3d443ded,0x3dd53d8e,0x3d15bdf5,0xbdc63da2,0xbdedbd44,0xbdfb3cc8,0x3d713de2,0x3c49bdff,
0x3d803d80,0x3db5bdb5,0xbdedbd44,0x3d443ded,0x3e000000,0xbdb53db5,0x3ded3d44,0xbd44bded,0xbe000000,0x3db5bdb5,0xbdedbd44,0x3d443ded,0x3e000000,0xbdb53db5,0x3ded3d44,0xbd44bded,
0xbd803d80,0xbdd53d8e,0x3de23d71,0xbc49bdff,0x3d443ded,0x3dfb3cc8,0xbd15bdf5,0xbda23dc6,0x3d44bded,0xbd8ebdd5,0xbd713de2,0x3dffbc49,0xbded3d44,0xbcc83dfb,0x3df5bd15,0xbdc6bda2,
0x3d803d80,0x3dedbd44,0xbdd5bd8e,0xbcc83dfb,0xbdb53db5,0xbd44bded,0xbd8e3dd5,0x3dfb3cc8,0x3db53db5,0xbded3d44,0x3dd53d8e,0x3cc8bdfb,0x3db5bdb5,0x3d443ded,0x3d8ebdd5,0xbdfbbcc8,
0xbd803d80,0xbdfb3cc8,0x3dc63da2,0x3d71bde2,0xbdedbd44,0xbd8e3dd5,0x3dffbc49,0xbd15bdf5,0xbded3d44,0x3cc83dfb,0x3da2bdc6,0xbde2bd71,0xbd443ded,0x3dd53d8e,0xbc49bdff,0xbdf53d15,
0x3d803d80,0x3e000000,0xbdb5bdb5,0xbdb53db5,0xbe00,0x3e000000,0xbdb5bdb5,0xbdb53db5,0xbe00,0x3e000000,0xbdb5bdb5,0xbdb53db5,0xbe00,0x3e000000,0xbdb5bdb5,0xbdb53db5,
0xbd803d80,0xbdfbbcc8,0x3da23dc6,0x3de2bd71,0x3dedbd44,0xbd8ebdd5,0xbc493dff,0x3df53d15,0x3ded3d44,0x3cc8bdfb,0xbdc63da2,0x3d713de2,0x3d443ded,0x3dd5bd8e,0xbdffbc49,0xbd153df5,
0x3d803d80,0x3ded3d44,0xbd8ebdd5,0xbdfb3cc8,0x3db53db5,0xbd443ded,0x3dd5bd8e,0xbcc8bdfb,0xbdb53db5,0xbdedbd44,0x3d8e3dd5,0x3dfbbcc8,0xbdb5bdb5,0x3d44bded,0xbdd53d8e,0x3cc83dfb,
0xbd803d80,0xbdd5bd8e,0x3d713de2,0x3dff3c49,0xbd443ded,0x3dfbbcc8,0xbdf5bd15,0xbdc63da2,0xbd44bded,0xbd8e3dd5,0x3de2bd71,0x3c49bdff,0x3ded3d44,0xbcc8bdfb,0xbd153df5,0x3da23dc6,
0x3d803d80,0x3db53db5,0xbd44bded,0xbdedbd44,0xbe000000,0xbdb5bdb5,0x3d443ded,0x3ded3d44,0x3e000000,0x3db53db5,0xbd44bded,0xbdedbd44,0xbe000000,0xbdb5bdb5,0x3d443ded,0x3ded3d44,
0xbd803d80,0xbd8ebdd5,0x3d153df5,0x3dc63da2,0xbd44bded,0xbcc83dfb,0x3d71bde2,0xbc49bdff,0xbd443ded,0x3dd5bd8e,0xbdf53d15,0xbda23dc6,0x3dedbd44,0xbdfbbcc8,0x3de23d71,0x3dffbc49,
0x3d803d80,0x3d443ded,0xbcc8bdfb,0xbd8ebdd5,0x3db5bdb5,0x3dedbd44,0xbdfb3cc8,0xbdd53d8e,0xbdb5bdb5,0xbd44bded,0x3cc83dfb,0x3d8e3dd5,0xbdb53db5,0xbded3d44,0x3dfbbcc8,0x3dd5bd8e,
0xbd803d80,0xbcc8bdfb,0x3c493dff,0x3d153df5,0x3ded3d44,0xbdd5bd8e,0x3dc63da2,0x3de23d71,0x3dedbd44,0xbdfb3cc8,0x3dffbc49,0x3df5bd15,0x3d44bded,0xbd8e3dd5,0x3da2bdc6,0x3d71bde2,
0xbc493dff,0xbbc93e00,0xbb493e00,0xbc173dff,0xbcc83dfb,0xbcf93df8,0xbce03dfa,0xbd093df7,0xbd443ded,0xbd5b3de7,0xbd4f3dea,0xbd663de5,0xbd8e3dd5,0xbd983dce,0xbd933dd1,0xbd9d3dca,
0xbd713de2,0xbcf93df8,0xbc7b3dfe,0xbd383def,0xbdd53d8e,0xbdf13d2c,0xbde53d66,0xbdfa3ce0,0xbdedbd44,0xbdcebd98,0xbddfbd7c,0xbdb9bdb1,0xbcc8bdfb,0x3bc9be00,0xbc17bdff,0x3cafbdfc,
0xbdc63da2,0xbd5b3de7,0xbce03dfa,0xbd9d3dca,0xbdfbbcc8,0xbdcebd98,0xbdeabd4f,0xbda7bdc2,0x3d44bded,0x3dbebdac,0x3d93bdd1,0x3ddfbd7c,0x3dd53d8e,0x3d843ddc,0x3db13db9,0x3d213df3,
0xbdf53d15,0xbd983dce,0xbd213df3,0xbdd13d93,0xbd8ebdd5,0x3bc9be00,0xbd09bdf7,0x3d38bdef,0x3ded3d44,0x3d843ddc,0x3dc23da7,0x3ce03dfa,0xbdfb3cc8,0xbde7bd5b,0xbdfebc7b,0xbdb9bdb1,
0xbdffbc49,0xbdbe3dac,0xbd4f3dea,0xbdf33d21,0x3cc8bdfb,0x3ddcbd84,0x3d93bdd1,0x3dfebc7b,0xbd443ded,0xbdf13d2c,0xbdb93db1,0xbdffbc17,0x3d8ebdd5,0x3dfdbc96,0x3dd8bd89,0x3df73d09,
0xbde2bd71,0xbddc3d84,0xbd7c3ddf,0xbe003b49,0x3dd5bd8e,0x3de73d5b,0x3dffbc17,0x3d933dd1,0xbdedbd44,0xbc96bdfd,0xbd9dbdca,0x3d38bdef,0x3cc83dfb,0xbdbe3dac,0xbd213df3,0xbdfa3ce0,
0xbda2bdc6,0xbdf13d2c,0xbd933dd1,0xbdf7bd09,0x3dfb3cc8,0x3c963dfd,0x3db13db9,0xbd663de5,0x3d44bded,0x3e003bc9,0x3dd8bd89,0x3dca3d9d,0xbdd5bd8e,0x3cf9bdf8,0xbd38bdef,0x3dc2bda7,
0xbd15bdf5,0xbdfd3c96,0xbda73dc2,0xbdd8bd89,0x3d8e3dd5,0xbdbe3dac,0xbc7b3dfe,0xbe003b49,0x3ded3d44,0xbcf93df8,0x3d663de5,0xbdd13d93,0x3dfbbcc8,0x3d2c3df1,0x3ddf3d7c,0xbd383def,
0x3c49bdff,0xbe00bbc9,0xbdb93db1,0xbda7bdc2,0xbcc83dfb,0xbdf8bcf9,0xbdd83d89,0xbd7cbddf,0xbd443ded,0xbde7bd5b,0xbdef3d38,0xbd21bdf3,0xbd8e3dd5,0xbdcebd98,0xbdfc3caf,0xbc7bbdfe,
0x3d71bde2,0xbdf8bcf9,0xbdca3d9d,0xbd4fbdea,0xbdd53d8e,0xbd2cbdf1,0xbdf3bd21,0x3d89bdd8,0xbdedbd44,0x3d98bdce,0xbd09bdf7,0x3e00bb49,0xbcc8bdfb,0x3e003bc9,0x3da7bdc2,0x3d933dd1,
0x3dc6bda2,0xbde7bd5b,0xbdd83d89,0xbc7bbdfe,0xbdfbbcc8,0x3d98bdce,0xbd38bdef,0x3dff3c17,0x3d44bded,0x3dac3dbe,0x3dfcbcaf,0xbd093df7,0x3dd53d8e,0xbddc3d84,0xbb493e00,0xbde5bd66,
0x3df5bd15,0xbdcebd98,0xbde53d66,0x3cafbdfc,0xbd8ebdd5,0x3e003bc9,0x3d7cbddf,0x3d4f3dea,0x3ded3d44,0xbddc3d84,0x3c173dff,0xbdd8bd89,0xbdfb3cc8,0x3d5bbde7,0xbd9dbdca,0x3e00bb49,
0x3dff3c49,0xbdacbdbe,0xbdef3d38,0x3d66bde5,0x3cc8bdfb,0x3d843ddc,0x3dfcbcaf,0xbd9d3dca,0xbd443ded,0xbd2cbdf1,0xbe00bb49,0x3dc2bda7,0x3d8ebdd5,0x3c963dfd,0x3dfa3ce0,0xbddf3d7c,
0x3de23d71,0xbd84bddc,0xbdf73d09,0x3db1bdb9,0x3dd5bd8e,0xbd5b3de7,0x3dc23da7,0xbdfcbcaf,0xbdedbd44,0x3dfdbc96,0x3c7bbdfe,0x3d4f3dea,0x3cc83dfb,0xbdacbdbe,0xbde53d66,0x3d89bdd8,
0x3da23dc6,0xbd2cbdf1,0xbdfc3caf,0x3ddfbd7c,0x3dfb3cc8,0xbdfd3c96,0xbb493e00,0xbd21bdf3,0x3d44bded,0xbbc93e00,0x3dfa3ce0,0xbdfe3c7b,0xbdd5bd8e,0x3df83cf9,0x3d4fbdea,0xbc173dff,
0x3d153df5,0xbc96bdfd,0xbdff3c17,0x3dfabce0,0x3d8e3dd5,0xbdacbdbe,0xbdca3d9d,0x3db1bdb9,0x3ded3d44,0xbdf8bcf9,0xbd213df3,0x3cafbdfc,0x3dfbbcc8,0xbdf13d2c,0x3d093df7,0xbd4fbdea,
0xbc493dff,0x3bc9be00,0xbe00bb49,0x3dff3c17,0xbcc83dfb,0x3cf9bdf8,0xbdfabce0,0x3df73d09,0xbd443ded,0x3d5bbde7,0xbdeabd4f,0x3de53d66,0xbd8e3dd5,0x3d98bdce,0xbdd1bd93,0x3dca3d9d,
0xbd713de2,0x3cf9bdf8,0xbdfebc7b,0x3def3d38,0xbdd53d8e,0x3df1bd2c,0xbd66bde5,0x3ce03dfa,0xbdedbd44,0x3dce3d98,0x3d7cbddf,0xbdb13db9,0xbcc8bdfb,0xbbc93e00,0x3dffbc17,0xbdfcbcaf,
0xbdc63da2,0x3d5bbde7,0xbdfabce0,0x3dca3d9d,0xbdfbbcc8,0x3dce3d98,0x3d4fbdea,0xbdc23da7,0x3d44bded,0xbdbe3dac,0x3dd13d93,0xbd7cbddf,0x3dd53d8e,0xbd84bddc,0xbdb93db1,0x3df3bd21,
0xbdf53d15,0x3d98bdce,0xbdf3bd21,0x3d933dd1,0xbd8ebdd5,0xbbc93e00,0x3df7bd09,0xbdefbd38,0x3ded3d44,0xbd84bddc,0xbda73dc2,0x3dfabce0,0xbdfb3cc8,0x3de73d5b,0x3c7bbdfe,0xbdb13db9,
0xbdffbc49,0x3dbebdac,0xbdeabd4f,0x3d213df3,0x3cc8bdfb,0xbddc3d84,0x3dd13d93,0xbc7bbdfe,0xbd443ded,0x3df1bd2c,0xbdb1bdb9,0xbc173dff,0x3d8ebdd5,0xbdfd3c96,0x3d893dd8,0x3d09bdf7,
0xbde2bd71,0x3ddcbd84,0xbddfbd7c,0x3b493e00,0x3dd5bd8e,0xbde7bd5b,0x3c173dff,0x3dd1bd93,0xbdedbd44,0x3c963dfd,0x3dcabd9d,0xbdefbd38,0x3cc83dfb,0x3dbebdac,0xbdf3bd21,0x3ce03dfa,
0xbda2bdc6,0x3df1bd2c,0xbdd1bd93,0xbd093df7,0x3dfb3cc8,0xbc96bdfd,0xbdb93db1,0x3de53d66,0x3d44bded,0xbe00bbc9,0x3d893dd8,0x3d9dbdca,0xbdd5bd8e,0xbcf93df8,0x3defbd38,0xbda7bdc2,
0xbd15bdf5,0x3dfdbc96,0xbdc2bda7,0xbd893dd8,0x3d8e3dd5,0x3dbebdac,0xbdfebc7b,0x3b493e00,0x3ded3d44,0x3cf9bdf8,0xbde53d66,0x3d933dd1,0x3dfbbcc8,0xbd2cbdf1,0xbd7c3ddf,0x3def3d38,
0x3c49bdff,0x3e003bc9,0xbdb1bdb9,0xbdc23da7,0xbcc83dfb,0x3df83cf9,0xbd89bdd8,0xbddf3d7c,0xbd443ded,0x3de73d5b,0xbd38bdef,0xbdf33d21,0xbd8e3dd5,0x3dce3d98,0xbcafbdfc,0xbdfe3c7b,
0x3d71bde2,0x3df83cf9,0xbd9dbdca,0xbdea3d4f,0xbdd53d8e,0x3d2c3df1,0x3d21bdf3,0xbdd8bd89,0xbdedbd44,0xbd983dce,0x3df7bd09,0xbb49be00,0xbcc8bdfb,0xbe00bbc9,0x3dc23da7,0x3dd1bd93,
0x3dc6bda2,0x3de73d5b,0xbd89bdd8,0xbdfe3c7b,0xbdfbbcc8,0xbd983dce,0x3defbd38,0x3c17bdff,0x3d44bded,0xbdacbdbe,0x3caf3dfc,0x3df73d09,0x3dd53d8e,0x3ddcbd84,0xbe00bb49,0xbd663de5,
0x3df5bd15,0x3dce3d98,0xbd66bde5,0xbdfcbcaf,0xbd8ebdd5,0xbe00bbc9,0x3ddf3d7c,0x3deabd4f,0x3ded3d44,0x3ddcbd84,0xbdff3c17,0xbd893dd8,0xbdfb3cc8,0xbd5b3de7,0x3dcabd9d,0xbb49be00,
0x3dff3c49,0x3dac3dbe,0xbd38bdef,0xbde5bd66,0x3cc8bdfb,0xbd84bddc,0x3caf3dfc,0x3dca3d9d,0xbd443ded,0x3d2c3df1,0x3b49be00,0xbda7bdc2,0x3d8ebdd5,0xbc96bdfd,0xbce03dfa,0x3d7c3ddf,
0x3de23d71,0x3d843ddc,0xbd09bdf7,0xbdb9bdb1,0x3dd5bd8e,0x3d5bbde7,0xbda73dc2,0xbcaf3dfc,0xbdedbd44,0xbdfd3c96,0x3dfe3c7b,0x3deabd4f,0x3cc83dfb,0x3dac3dbe,0xbd66bde5,0xbdd8bd89,
0x3da23dc6,0x3d2c3df1,0xbcafbdfc,0xbd7cbddf,0x3dfb3cc8,0x3dfdbc96,0xbe00bb49,0xbdf33d21,0x3d44bded,0x3bc9be00,0xbce03dfa,0x3c7b3dfe,0xbdd5bd8e,0xbdf8bcf9,0x3dea3d4f,0x3dff3c17,
0x3d153df5,0x3c963dfd,0xbc17bdff,0xbce0bdfa,0x3d8e3dd5,0x3dac3dbe,0xbd9dbdca,0xbdb9bdb1,0x3ded3d44,0x3df83cf9,0xbdf3bd21,0xbdfcbcaf,0x3dfbbcc8,0x3df1bd2c,0xbdf73d09,0xbdea3d4f,
0xbdb53d80,0xbdbe3dac,0xbdb93db1,0xbdc23da7,0xbd153df5,0xbddc3d84,0xbdd83d89,0xbddf3d7c,0xbd713de2,0xbdf13d2c,0xbdef3d38,0xbdf33d21,0xbda23dc6,0xbdfd3c96,0xbdfc3caf,0xbdfe3c7b,
0x3db53d80,0x3ddcbd84,0x3dcabd9d,0x3deabd4f,0xbdff3c49,0x3de73d5b,0x3df33d21,0x3dd83d89,0xbda2bdc6,0x3c963dfd,0x3d093df7,0x3b493e00,0x3d15bdf5,0xbdbe3dac,0xbda73dc2,0xbdd13d93,
0xbdb53d80,0xbdf13d2c,0xbdd83d89,0xbdfe3c7b,0xbd71bde2,0xbc96bdfd,0xbd38bdef,0x3c17bdff,0x3df5bd15,0x3e003bc9,0x3dfcbcaf,0x3df73d09,0x3c493dff,0xbcf93df8,0xbb493e00,0xbd663de5,
0x3db53d80,0x3dfdbc96,0x3de5bd66,0x3dfc3caf,0x3da2bdc6,0xbdbe3dac,0xbd7c3ddf,0xbdea3d4f,0xbc493dff,0x3cf9bdf8,0xbc17bdff,0x3d89bdd8,0xbd71bde2,0x3d2c3df1,0x3d9d3dca,0x3b493e00,
0xbdb53d80,0xbe00bbc9,0xbdef3d38,0xbde5bd66,0x3df53d15,0x3df83cf9,0x3dfcbcaf,0x3dca3d9d,0xbde2bd71,0xbde7bd5b,0xbe00bb49,0xbda7bdc2,0x3dc63da2,0x3dce3d98,0x3dfa3ce0,0x3d7c3ddf,
0x3db53d80,0x3df83cf9,0x3df7bd09,0x3db93db1,0x3c493dff,0xbd2cbdf1,0xbdc2bda7,0x3cafbdfc,0x3dc6bda2,0xbd983dce,0xbc7b3dfe,0xbdea3d4f,0xbdf5bd15,0x3e003bc9,0x3de5bd66,0x3dd83d89,
0xbdb53d80,0xbde7bd5b,0xbdfc3caf,0xbd7cbddf,0xbde23d71,0xbd983dce,0xbb493e00,0xbdf33d21,0x3d153df5,0x3dac3dbe,0x3dfa3ce0,0x3c7b3dfe,0x3dffbc49,0x3ddcbd84,0x3d4fbdea,0x3dff3c17,
0x3db53d80,0x3dce3d98,0x3dffbc17,0x3ce03dfa,0xbdc6bda2,0x3e003bc9,0x3dcabd9d,0x3db93db1,0xbdffbc49,0x3ddcbd84,0x3d21bdf3,0x3dfc3caf,0xbde23d71,0x3d5bbde7,0xbd09bdf7,0x3deabd4f,
0xbdb53d80,0xbdacbdbe,0xbe00bb49,0x3c17bdff,0x3d15bdf5,0xbd84bddc,0xbdfabce0,0x3d09bdf7,0x3d71bde2,0xbd2cbdf1,0xbdeabd4f,0x3d66bde5,0x3da2bdc6,0xbc96bdfd,0xbdd1bd93,0x3d9dbdca,
0x3db53d80,0x3d843ddc,0x3dfe3c7b,0xbd383def,0x3dffbc49,0xbd5b3de7,0x3d663de5,0xbdfa3ce0,0x3da23dc6,0xbdfd3c96,0xbd7c3ddf,0xbdb9bdb1,0xbd153df5,0xbdacbdbe,0xbdff3c17,0x3cafbdfc,
0xbdb53d80,0xbd2cbdf1,0xbdfabce0,0x3d9dbdca,0x3d713de2,0x3dfdbc96,0x3d4fbdea,0x3da73dc2,0xbdf53d15,0xbbc93e00,0x3dd13d93,0xbddf3d7c,0xbc49bdff,0xbdf8bcf9,0xbdb93db1,0xbd21bdf3,
0x3db53d80,0x3c963dfd,0x3df33d21,0xbdd13d93,0xbda23dc6,0xbdacbdbe,0xbdf73d09,0x3d38bdef,0x3c49bdff,0x3df83cf9,0x3da7bdc2,0x3ce03dfa,0x3d713de2,0xbdf13d2c,0xbc7b3dfe,0xbdb9bdb1,
0xbdb53d80,0x3bc9be00,0xbdeabd4f,0x3df3bd21,0xbdf5bd15,0xbcf93df8,0x3dd13d93,0xbdfe3c7b,0x3de23d71,0x3d5bbde7,0xbdb1bdb9,0x3dff3c17,0xbdc6bda2,0xbd983dce,0x3d893dd8,0xbdf7bd09,
0x3db53d80,0xbcf93df8,0x3ddf3d7c,0xbe003b49,0xbc49bdff,0x3df1bd2c,0xbc17bdff,0x3d933dd1,0xbdc63da2,0xbdcebd98,0xbdca3d9d,0x3d38bdef,0x3df53d15,0xbbc93e00,0x3df33d21,0xbdfa3ce0,
0xbdb53d80,0x3d5bbde7,0xbdd1bd93,0x3df73d09,0x3de2bd71,0xbdcebd98,0xbdb93db1,0x3d66bde5,0xbd15bdf5,0xbdbe3dac,0x3d893dd8,0xbdcabd9d,0xbdff3c49,0x3d843ddc,0x3defbd38,0xbdc23da7,
0x3db53d80,0xbd983dce,0x3dc23da7,0xbdd8bd89,0x3dc63da2,0xbbc93e00,0x3dfe3c7b,0xbe003b49,0x3dff3c49,0x3d843ddc,0x3de5bd66,0xbdd13d93,0x3de2bd71,0x3de73d5b,0x3d7cbddf,0xbd383def,
0xbdb53d80,0x3dbebdac,0xbdb1bdb9,0x3da73dc2,0xbd153df5,0x3ddcbd84,0xbd89bdd8,0x3d7c3ddf,0xbd713de2,0x3df1bd2c,0xbd38bdef,0x3d213df3,0xbda23dc6,0x3dfdbc96,0xbcafbdfc,0x3c7b3dfe,
0x3db53d80,0xbddc3d84,0x3d9d3dca,0xbd4fbdea,0xbdff3c49,0xbde7bd5b,0xbd213df3,0x3d89bdd8,0xbda2bdc6,0xbc96bdfd,0xbdf73d09,0x3e00bb49,0x3d15bdf5,0x3dbebdac,0xbdc2bda7,0x3d933dd1,
0xbdb53d80,0x3df1bd2c,0xbd89bdd8,0x3c7b3dfe,0xbd71bde2,0x3c963dfd,0x3defbd38,0xbdffbc17,0x3df5bd15,0xbe00bbc9,0x3caf3dfc,0x3d09bdf7,0x3c493dff,0x3cf9bdf8,0xbe00bb49,0x3de53d66,
0x3db53d80,0xbdfd3c96,0x3d663de5,0x3cafbdfc,0x3da2bdc6,0x3dbebdac,0xbddfbd7c,0x3d4f3dea,0xbc493dff,0xbcf93df8,0x3dffbc17,0xbdd8bd89,0xbd71bde2,0xbd2cbdf1,0xbdca3d9d,0x3e00bb49,
0xbdb53d80,0x3e003bc9,0xbd38bdef,0xbd663de5,0x3df53d15,0xbdf8bcf9,0x3caf3dfc,0x3d9dbdca,0xbde2bd71,0x3de73d5b,0x3b49be00,0xbdc23da7,0x3dc63da2,0xbdcebd98,0xbce03dfa,0x3ddfbd7c,
0x3db53d80,0xbdf8bcf9,0x3d093df7,0x3db1bdb9,0x3c493dff,0x3d2c3df1,0x3da7bdc2,0xbdfcbcaf,0x3dc6bda2,0x3d98bdce,0xbdfebc7b,0x3d4f3dea,0xbdf5bd15,0xbe00bbc9,0x3d663de5,0x3d89bdd8,
0xbdb53d80,0x3de73d5b,0xbcafbdfc,0xbddf3d7c,0xbde23d71,0x3d98bdce,0xbe00bb49,0x3d213df3,0x3d153df5,0xbdacbdbe,0xbce03dfa,0x3dfebc7b,0x3dffbc49,0xbddc3d84,0x3dea3d4f,0x3c17bdff,
0x3db53d80,0xbdcebd98,0x3c173dff,0x3dfabce0,0xbdc6bda2,0xbe00bbc9,0x3d9d3dca,0x3db1bdb9,0xbdffbc49,0xbddc3d84,0x3df33d21,0x3cafbdfc,0xbde23d71,0xbd5b3de7,0x3df7bd09,0xbd4fbdea,
0xbdb53d80,0x3dac3dbe,0x3b49be00,0xbdffbc17,0x3d15bdf5,0x3d843ddc,0x3ce0bdfa,0xbdf7bd09,0x3d71bde2,0x3d2c3df1,0x3d4fbdea,0xbde5bd66,0x3da2bdc6,0x3c963dfd,0x3d93bdd1,0xbdcabd9d,
0x3db53d80,0xbd84bddc,0xbc7b3dfe,0x3def3d38,0x3dffbc49,0x3d5bbde7,0xbde53d66,0x3ce03dfa,0x3da23dc6,0x3dfdbc96,0xbddfbd7c,0xbdb13db9,0xbd153df5,0x3dac3dbe,0xbc17bdff,0xbdfcbcaf,
0xbdb53d80,0x3d2c3df1,0x3ce0bdfa,0xbdcabd9d,0x3d713de2,0xbdfd3c96,0x3dea3d4f,0x3dc2bda7,0xbdf53d15,0x3bc9be00,0xbd933dd1,0x3d7c3ddf,0xbc49bdff,0x3df83cf9,0xbdb1bdb9,0xbdf33d21,
0x3db53d80,0xbc96bdfd,0xbd213df3,0x3d933dd1,0xbda23dc6,0x3dac3dbe,0xbd09bdf7,0xbdefbd38,0x3c49bdff,0xbdf8bcf9,0x3dc23da7,0x3dfabce0,0x3d713de2,0x3df1bd2c,0xbdfebc7b,0xbdb13db9,
0xbdb53d80,0xbbc93e00,0x3d4fbdea,0xbd21bdf3,0xbdf5bd15,0x3cf9bdf8,0xbd933dd1,0x3c7b3dfe,0x3de23d71,0xbd5b3de7,0x3db9bdb1,0x3c17bdff,0xbdc6bda2,0x3d98bdce,0xbdd83d89,0xbd093df7,
0x3db53d80,0x3cf9bdf8,0xbd7c3ddf,0x3b493e00,0xbc49bdff,0xbdf13d2c,0x3dffbc17,0x3dd1bd93,0xbdc63da2,0x3dce3d98,0xbd9dbdca,0xbdefbd38,0x3df53d15,0x3bc9be00,0xbd213df3,0x3ce03dfa,
0xbdb53d80,0xbd5b3de7,0x3d93bdd1,0x3d09bdf7,0x3de2bd71,0x3dce3d98,0xbdb1bdb9,0xbde5bd66,0xbd15bdf5,0x3dbebdac,0xbdd83d89,0xbd9d3dca,0xbdff3c49,0xbd84bddc,0x3d383def,0x3da73dc2,
0x3db53d80,0x3d98bdce,0xbda73dc2,0xbd893dd8,0x3dc63da2,0x3bc9be00,0xbc7b3dfe,0x3b493e00,0x3dff3c49,0xbd84bddc,0x3d663de5,0x3d933dd1,0x3de2bd71,0xbde7bd5b,0x3ddf3d7c,0x3def3d38,
0xbcc83dfb,0xbc493dff,0xbbc93e00,0xbc963dfd,0xbd443ded,0xbd713de2,0xbd5b3de7,0xbd843ddc,0xbdb53db5,0xbdc63da2,0xbdbe3dac,0xbdce3d98,0xbded3d44,0xbdf53d15,0xbdf13d2c,0xbdf83cf9,
0xbd8e3dd5,0xbd153df5,0xbc963dfd,0xbd5b3de7,0xbded3d44,0xbdff3c49,0xbdf83cf9,0xbe00bbc9,0xbdb5bdb5,0xbd71bde2,0xbd98bdce,0xbd2cbdf1,0x3d44bded,0x3da2bdc6,0x3d84bddc,0x3dbebdac,
0xbdd53d8e,0xbd713de2,0xbcf93df8,0xbdac3dbe,0xbdedbd44,0xbda2bdc6,0xbdcebd98,0xbd5bbde7,0x3db5bdb5,0x3df5bd15,0x3ddcbd84,0x3e00bbc9,0x3d443ded,0xbc493dff,0x3c963dfd,0xbd2c3df1,
0xbdfb3cc8,0xbda23dc6,0xbd2c3df1,0xbddc3d84,0xbd44bded,0x3d15bdf5,0xbbc9be00,0x3d98bdce,0x3db53db5,0x3c493dff,0x3d5b3de7,0xbcf93df8,0xbdedbd44,0xbd71bde2,0xbdbebdac,0xbc96bdfd,
0xbdfbbcc8,0xbdc63da2,0xbd5b3de7,0xbdf83cf9,0x3d44bded,0x3df5bd15,0x3dbebdac,0x3dfd3c96,0xbdb53db5,0xbdffbc49,0xbdf13d2c,0xbddcbd84,0x3dedbd44,0x3de23d71,0x3e003bc9,0x3d983dce,
0xbdd5bd8e,0xbde23d71,0xbd843ddc,0xbe00bbc9,0x3dedbd44,0x3dc63da2,0x3dfd3c96,0x3d2c3df1,0xbdb5bdb5,0x3d15bdf5,0xbcf9bdf8,0x3dbebdac,0xbd443ded,0xbdff3c49,0xbdce3d98,0xbde7bd5b,
0xbd8ebdd5,0xbdf53d15,0xbd983dce,0xbdf1bd2c,0x3ded3d44,0xbc493dff,0x3d843ddc,0xbdac3dbe,0x3db5bdb5,0x3de23d71,0x3dfdbc96,0x3d5b3de7,0xbd44bded,0x3dc6bda2,0x3cf9bdf8,0x3e00bbc9,
0xbcc8bdfb,0xbdff3c49,0xbdac3dbe,0xbdcebd98,0x3d443ded,0xbde23d71,0xbd2c3df1,0xbdf8bcf9,0x3db53db5,0xbda23dc6,0x3bc93e00,0xbdfd3c96,0x3ded3d44,0xbd153df5,0x3d5b3de7,0xbddc3d84,
0x3cc8bdfb,0xbdffbc49,0xbdbe3dac,0xbd98bdce,0xbd443ded,0xbde2bd71,0xbdf13d2c,0xbcf9bdf8,0xbdb53db5,0xbda2bdc6,0xbe00bbc9,0x3c96bdfd,0xbded3d44,0xbd15bdf5,0xbde7bd5b,0x3d84bddc,
0x3d8ebdd5,0xbdf5bd15,0xbdce3d98,0xbd2cbdf1,0xbded3d44,0xbc49bdff,0xbddcbd84,0x3dbebdac,0xbdb5bdb5,0x3de2bd71,0x3c96bdfd,0x3de73d5b,0x3d44bded,0x3dc63da2,0x3df8bcf9,0xbbc93e00,
0x3dd5bd8e,0xbde2bd71,0xbddc3d84,0xbbc9be00,0xbdedbd44,0x3dc6bda2,0xbc96bdfd,0x3df13d2c,0x3db5bdb5,0x3d153df5,0x3df83cf9,0xbdac3dbe,0x3d443ded,0xbdffbc49,0xbd983dce,0xbd5bbde7,
0x3dfbbcc8,0xbdc6bda2,0xbde73d5b,0x3cf9bdf8,0xbd44bded,0x3df53d15,0x3dacbdbe,0x3c963dfd,0x3db53db5,0xbdff3c49,0xbd2c3df1,0xbd84bddc,0xbdedbd44,0x3de2bd71,0xbbc9be00,0x3dce3d98,
0x3dfb3cc8,0xbda2bdc6,0xbdf13d2c,0x3d84bddc,0x3d44bded,0x3d153df5,0x3e003bc9,0xbdce3d98,0xbdb53db5,0x3c49bdff,0xbde7bd5b,0x3df8bcf9,0x3dedbd44,0xbd713de2,0x3dac3dbe,0xbdfdbc96,
0x3dd53d8e,0xbd71bde2,0xbdf83cf9,0x3dbebdac,0x3dedbd44,0xbda23dc6,0x3d983dce,0xbde7bd5b,0xbdb5bdb5,0x3df53d15,0x3d84bddc,0xbbc93e00,0xbd443ded,0xbc49bdff,0xbdfdbc96,0x3df1bd2c,
0x3d8e3dd5,0xbd15bdf5,0xbdfd3c96,0x3de7bd5b,0x3ded3d44,0xbdffbc49,0xbcf93df8,0xbbc9be00,0x3db5bdb5,0xbd713de2,0x3dce3d98,0xbdf1bd2c,0xbd44bded,0x3da23dc6,0x3ddcbd84,0xbdac3dbe,
0x3cc83dfb,0xbc49bdff,0xbe003bc9,0x3dfdbc96,0x3d443ded,0xbd71bde2,0xbde73d5b,0x3ddcbd84,0x3db53db5,0xbdc6bda2,0xbdac3dbe,0x3d98bdce,0x3ded3d44,0xbdf5bd15,0xbd2c3df1,0x3cf9bdf8,
0xbcc83dfb,0x3c49bdff,0xbe00bbc9,0x3dfd3c96,0xbd443ded,0x3d71bde2,0xbde7bd5b,0x3ddc3d84,0xbdb53db5,0x3dc6bda2,0xbdacbdbe,0x3d983dce,0xbded3d44,0x3df5bd15,0xbd2cbdf1,0x3cf93df8,
0xbd8e3dd5,0x3d15bdf5,0xbdfdbc96,0x3de73d5b,0xbded3d44,0x3dffbc49,0xbcf9bdf8,0xbbc93e00,0xbdb5bdb5,0x3d713de2,0x3dcebd98,0xbdf13d2c,0x3d44bded,0xbda23dc6,0x3ddc3d84,0xbdacbdbe,
0xbdd53d8e,0x3d71bde2,0xbdf8bcf9,0x3dbe3dac,0xbdedbd44,0x3da23dc6,0x3d98bdce,0xbde73d5b,0x3db5bdb5,0xbdf53d15,0x3d843ddc,0xbbc9be00,0x3d443ded,0x3c49bdff,0xbdfd3c96,0x3df13d2c,
0xbdfb3cc8,0x3da2bdc6,0xbdf1bd2c,0x3d843ddc,0xbd44bded,0xbd153df5,0x3e00bbc9,0xbdcebd98,0x3db53db5,0xbc49bdff,0xbde73d5b,0x3df83cf9,0xbdedbd44,0x3d713de2,0x3dacbdbe,0xbdfd3c96,
0xbdfbbcc8,0x3dc6bda2,0xbde7bd5b,0x3cf93df8,0x3d44bded,0xbdf53d15,0x3dac3dbe,0x3c96bdfd,0xbdb53db5,0x3dff3c49,0xbd2cbdf1,0xbd843ddc,0x3dedbd44,0xbde2bd71,0xbbc93e00,0x3dcebd98,
0xbdd5bd8e,0x3de2bd71,0xbddcbd84,0xbbc93e00,0x3dedbd44,0xbdc6bda2,0xbc963dfd,0x3df1bd2c,0xbdb5bdb5,0xbd153df5,0x3df8bcf9,0xbdacbdbe,0xbd443ded,0x3dffbc49,0xbd98bdce,0xbd5b3de7,
0xbd8ebdd5,0x3df5bd15,0xbdcebd98,0xbd2c3df1,0x3ded3d44,0x3c49bdff,0xbddc3d84,0x3dbe3dac,0x3db5bdb5,0xbde2bd71,0x3c963dfd,0x3de7bd5b,0xbd44bded,0xbdc63da2,0x3df83cf9,0xbbc9be00,
0xbcc8bdfb,0x3dffbc49,0xbdbebdac,0xbd983dce,0x3d443ded,0x3de2bd71,0xbdf1bd2c,0xbcf93df8,0x3db53db5,0x3da2bdc6,0xbe003bc9,0x3c963dfd,0x3ded3d44,0x3d15bdf5,0xbde73d5b,0x3d843ddc,
0x3cc8bdfb,0x3dff3c49,0xbdacbdbe,0xbdce3d98,0xbd443ded,0x3de23d71,0xbd2cbdf1,0xbdf83cf9,0xbdb53db5,0x3da23dc6,0x3bc9be00,0xbdfdbc96,0xbded3d44,0x3d153df5,0x3d5bbde7,0xbddcbd84,
0x3d8ebdd5,0x3df53d15,0xbd98bdce,0xbdf13d2c,0xbded3d44,0x3c493dff,0x3d84bddc,0xbdacbdbe,0xbdb5bdb5,0xbde23d71,0x3dfd3c96,0x3d5bbde7,0x3d44bded,0xbdc6bda2,0x3cf93df8,0x3e003bc9,
0x3dd5bd8e,0x3de23d71,0xbd84bddc,0xbe003bc9,0xbdedbd44,0xbdc63da2,0x3dfdbc96,0x3d2cbdf1,0x3db5bdb5,0xbd15bdf5,0xbcf93df8,0x3dbe3dac,0x3d443ded,0x3dff3c49,0xbdcebd98,0xbde73d5b,
0x3dfbbcc8,0x3dc63da2,0xbd5bbde7,0xbdf8bcf9,0xbd44bded,0xbdf5bd15,0x3dbe3dac,0x3dfdbc96,0x3db53db5,0x3dffbc49,0xbdf1bd2c,0xbddc3d84,0xbdedbd44,0xbde23d71,0x3e00bbc9,0x3d98bdce,
0x3dfb3cc8,0x3da23dc6,0xbd2cbdf1,0xbddcbd84,0x3d44bded,0xbd15bdf5,0xbbc93e00,0x3d983dce,0xbdb53db5,0xbc493dff,0x3d5bbde7,0xbcf9bdf8,0x3dedbd44,0x3d71bde2,0xbdbe3dac,0xbc963dfd,
0x3dd53d8e,0x3d713de2,0xbcf9bdf8,0xbdacbdbe,0x3dedbd44,0x3da2bdc6,0xbdce3d98,0xbd5b3de7,0xbdb5bdb5,0xbdf5bd15,0x3ddc3d84,0x3e003bc9,0xbd443ded,0x3c493dff,0x3c96bdfd,0xbd2cbdf1,
0x3d8e3dd5,0x3d153df5,0xbc96bdfd,0xbd5bbde7,0x3ded3d44,0x3dff3c49,0xbdf8bcf9,0xbe003bc9,0x3db5bdb5,0x3d71bde2,0xbd983dce,0xbd2c3df1,0xbd44bded,0xbda2bdc6,0x3d843ddc,0x3dbe3dac,
0x3cc83dfb,0x3c493dff,0xbbc9be00,0xbc96bdfd,0x3d443ded,0x3d713de2,0xbd5bbde7,0xbd84bddc,0x3db53db5,0x3dc63da2,0xbdbebdac,0xbdcebd98,0x3ded3d44,0x3df53d15,0xbdf1bd2c,0xbdf8bcf9,
0xbd803d80,0xbdffbc49,0xbe00bbc9,0xbdfdbc96,0xbd8e3dd5,0xbde2bd71,0xbde7bd5b,0xbddcbd84,0xbdd53d8e,0xbda2bdc6,0xbdacbdbe,0xbd98bdce,0xbdfb3cc8,0xbd15bdf5,0xbd2cbdf1,0xbcf9bdf8,
0x3d803d80,0x3df53d15,0x3dfd3c96,0x3de73d5b,0xbdfbbcc8,0x3c493dff,0x3cf93df8,0xbbc93e00,0xbcc8bdfb,0xbde23d71,0xbdce3d98,0xbdf13d2c,0x3dd5bd8e,0xbdc6bda2,0xbddcbd84,0xbdacbdbe,
0xbd803d80,0xbde2bd71,0xbdf8bcf9,0xbdbebdac,0xbcc8bdfb,0x3dc6bda2,0x3d98bdce,0x3de7bd5b,0x3dfb3cc8,0x3d153df5,0x3d843ddc,0x3bc93e00,0xbd8e3dd5,0xbdffbc49,0xbdfd3c96,0xbdf1bd2c,
0x3d803d80,0x3dc63da2,0x3df13d2c,0x3d843ddc,0x3dd5bd8e,0xbdf5bd15,0xbe003bc9,0xbdcebd98,0xbd8e3dd5,0x3dffbc49,0x3de7bd5b,0x3df83cf9,0x3cc8bdfb,0xbde23d71,0xbdac3dbe,0xbdfd3c96,
0xbd803d80,0xbda2bdc6,0xbde7bd5b,0xbcf9bdf8,0x3dd53d8e,0x3d153df5,0x3dac3dbe,0xbc963dfd,0xbd8ebdd5,0x3c49bdff,0xbd2cbdf1,0x3d84bddc,0x3cc83dfb,0xbd713de2,0xbbc93e00,0xbdce3d98,
0x3d803d80,0x3d713de2,0x3ddc3d84,0xbbc93e00,0xbcc83dfb,0x3da2bdc6,0x3c96bdfd,0x3df1bd2c,0x3dfbbcc8,0xbdf5bd15,0xbdf83cf9,0xbdacbdbe,0xbd8ebdd5,0x3c493dff,0x3d983dce,0xbd5b3de7,
0xbd803d80,0xbd15bdf5,0xbdcebd98,0x3d2cbdf1,0xbdfb3cc8,0xbdffbc49,0xbddc3d84,0xbdbebdac,0xbcc83dfb,0xbd713de2,0x3c963dfd,0xbde73d5b,0x3dd53d8e,0x3da23dc6,0x3df83cf9,0x3bc93e00,
0x3d803d80,0x3c493dff,0x3dbe3dac,0xbd983dce,0xbd8ebdd5,0x3d713de2,0x3df13d2c,0xbcf93df8,0xbdd5bd8e,0x3dc63da2,0x3e00bbc9,0x3c963dfd,0xbdfbbcc8,0x3df53d15,0x3de7bd5b,0x3d843ddc,
0xbd803d80,0x3c49bdff,0xbdacbdbe,0x3dcebd98,0x3d8ebdd5,0x3d71bde2,0xbd2cbdf1,0x3df8bcf9,0x3dd5bd8e,0x3dc6bda2,0x3bc9be00,0x3dfd3c96,0x3dfbbcc8,0x3df5bd15,0x3d5bbde7,0x3ddc3d84,
0x3d803d80,0xbd153df5,0x3d983dce,0xbdf13d2c,0x3dfb3cc8,0xbdff3c49,0xbd843ddc,0xbdacbdbe,0x3cc83dfb,0xbd71bde2,0xbdfdbc96,0x3d5bbde7,0xbdd53d8e,0x3da2bdc6,0xbcf9bdf8,0x3e003bc9,
0xbd803d80,0x3d71bde2,0xbd84bddc,0x3e00bbc9,0x3cc83dfb,0x3da23dc6,0x3dfdbc96,0xbd2c3df1,0xbdfbbcc8,0xbdf53d15,0xbcf93df8,0xbdbebdac,0x3d8ebdd5,0x3c49bdff,0xbdcebd98,0x3de7bd5b,
0x3d803d80,0xbda23dc6,0x3d5b3de7,0xbdf8bcf9,0xbdd53d8e,0x3d15bdf5,0xbdbebdac,0x3dfdbc96,0x3d8ebdd5,0x3c493dff,0x3df13d2c,0xbddc3d84,0xbcc83dfb,0xbd71bde2,0xbe003bc9,0x3d98bdce,
0xbd803d80,0x3dc6bda2,0xbd2cbdf1,0x3ddc3d84,0xbdd5bd8e,0xbdf53d15,0xbbc93e00,0xbd98bdce,0x3d8e3dd5,0x3dff3c49,0x3d5bbde7,0x3cf93df8,0xbcc8bdfb,0xbde2bd71,0xbdbe3dac,0x3c96bdfd,
0x3d803d80,0xbde23d71,0x3cf93df8,0xbdacbdbe,0x3cc8bdfb,0x3dc63da2,0x3dcebd98,0xbd5b3de7,0xbdfb3cc8,0x3d15bdf5,0xbddcbd84,0x3e003bc9,0x3d8e3dd5,0xbdff3c49,0xbc963dfd,0xbd2cbdf1,
0xbd803d80,0x3df5bd15,0xbc96bdfd,0x3d5b3de7,0x3dfbbcc8,0x3c49bdff,0xbdf8bcf9,0x3e00bbc9,0x3cc8bdfb,0xbde2bd71,0xbd983dce,0x3d2cbdf1,0xbdd5bd8e,0xbdc63da2,0x3d843ddc,0xbdbebdac,
0x3d803d80,0xbdff3c49,0x3bc93e00,0xbc96bdfd,0x3d8e3dd5,0xbde23d71,0x3d5b3de7,0xbd84bddc,0x3dd53d8e,0xbda23dc6,0x3dbe3dac,0xbdcebd98,0x3dfb3cc8,0xbd153df5,0x3df13d2c,0xbdf8bcf9,
0xbd803d80,0x3dff3c49,0x3bc9be00,0xbc963dfd,0xbd8e3dd5,0x3de23d71,0x3d5bbde7,0xbd843ddc,0xbdd53d8e,0x3da23dc6,0x3dbebdac,0xbdce3d98,0xbdfb3cc8,0x3d153df5,0x3df1bd2c,0xbdf83cf9,
0x3d803d80,0xbdf5bd15,0xbc963dfd,0x3d5bbde7,0xbdfbbcc8,0xbc49bdff,0xbdf83cf9,0x3e003bc9,0xbcc8bdfb,0x3de2bd71,0xbd98bdce,0x3d2c3df1,0x3dd5bd8e,0x3dc63da2,0x3d84bddc,0xbdbe3dac,
0xbd803d80,0x3de23d71,0x3cf9bdf8,0xbdac3dbe,0xbcc8bdfb,0xbdc63da2,0x3dce3d98,0xbd5bbde7,0x3dfb3cc8,0xbd15bdf5,0xbddc3d84,0x3e00bbc9,0xbd8e3dd5,0x3dff3c49,0xbc96bdfd,0xbd2c3df1,
0x3d803d80,0xbdc6bda2,0xbd2c3df1,0x3ddcbd84,0x3dd5bd8e,0x3df53d15,0xbbc9be00,0xbd983dce,0xbd8e3dd5,0xbdff3c49,0x3d5b3de7,0x3cf9bdf8,0x3cc8bdfb,0x3de2bd71,0xbdbebdac,0x3c963dfd,
0xbd803d80,0x3da23dc6,0x3d5bbde7,0xbdf83cf9,0x3dd53d8e,0xbd15bdf5,0xbdbe3dac,0x3dfd3c96,0xbd8ebdd5,0xbc493dff,0x3df1bd2c,0xbddcbd84,0x3cc83dfb,0x3d71bde2,0xbe00bbc9,0x3d983dce,
0x3d803d80,0xbd71bde2,0xbd843ddc,0x3e003bc9,0xbcc83dfb,0xbda23dc6,0x3dfd3c96,0xbd2cbdf1,0x3dfbbcc8,0x3df53d15,0xbcf9bdf8,0xbdbe3dac,0xbd8ebdd5,0xbc49bdff,0xbdce3d98,0x3de73d5b,
0xbd803d80,0x3d153df5,0x3d98bdce,0xbdf1bd2c,0xbdfb3cc8,0x3dff3c49,0xbd84bddc,0xbdac3dbe,0xbcc83dfb,0x3d71bde2,0xbdfd3c96,0x3d5b3de7,0x3dd53d8e,0xbda2bdc6,0xbcf93df8,0x3e00bbc9,
0x3d803d80,0xbc49bdff,0xbdac3dbe,0x3dce3d98,0xbd8ebdd5,0xbd71bde2,0xbd2c3df1,0x3df83cf9,0xbdd5bd8e,0xbdc6bda2,0x3bc93e00,0x3dfdbc96,0xbdfbbcc8,0xbdf5bd15,0x3d5b3de7,0x3ddcbd84,
0xbd803d80,0xbc493dff,0x3dbebdac,0xbd98bdce,0x3d8ebdd5,0xbd713de2,0x3df1bd2c,0xbcf9bdf8,0x3dd5bd8e,0xbdc63da2,0x3e003bc9,0x3c96bdfd,0x3dfbbcc8,0xbdf53d15,0x3de73d5b,0x3d84bddc,
0x3d803d80,0x3d15bdf5,0xbdce3d98,0x3d2c3df1,0x3dfb3cc8,0x3dffbc49,0xbddcbd84,0xbdbe3dac,0x3cc83dfb,0x3d713de2,0x3c96bdfd,0xbde7bd5b,0xbdd53d8e,0xbda23dc6,0x3df8bcf9,0x3bc9be00,
0xbd803d80,0xbd713de2,0x3ddcbd84,0xbbc9be00,0x3cc83dfb,0xbda2bdc6,0x3c963dfd,0x3df13d2c,0xbdfbbcc8,0x3df5bd15,0xbdf8bcf9,0xbdac3dbe,0x3d8ebdd5,0xbc493dff,0x3d98bdce,0xbd5bbde7,
0x3d803d80,0x3da2bdc6,0xbde73d5b,0xbcf93df8,0xbdd53d8e,0xbd153df5,0x3dacbdbe,0xbc96bdfd,0x3d8ebdd5,0xbc49bdff,0xbd2c3df1,0x3d843ddc,0xbcc83dfb,0x3d713de2,0xbbc9be00,0xbdcebd98,
0xbd803d80,0xbdc63da2,0x3df1bd2c,0x3d84bddc,0xbdd5bd8e,0x3df5bd15,0xbe00bbc9,0xbdce3d98,0x3d8e3dd5,0xbdffbc49,0x3de73d5b,0x3df8bcf9,0xbcc8bdfb,0x3de23d71,0xbdacbdbe,0xbdfdbc96,
0x3d803d80,0x3de2bd71,0xbdf83cf9,0xbdbe3dac,0x3cc8bdfb,0xbdc6bda2,0x3d983dce,0x3de73d5b,0xbdfb3cc8,0xbd153df5,0x3d84bddc,0x3bc9be00,0x3d8e3dd5,0x3dffbc49,0xbdfdbc96,0xbdf13d2c,
0xbd803d80,0xbdf53d15,0x3dfdbc96,0x3de7bd5b,0x3dfbbcc8,0xbc493dff,0x3cf9bdf8,0xbbc9be00,0x3cc8bdfb,0x3de23d71,0xbdcebd98,0xbdf1bd2c,0xbdd5bd8e,0x3dc6bda2,0xbddc3d84,0xbdac3dbe,
0x3d803d80,0x3dffbc49,0xbe003bc9,0xbdfd3c96,0x3d8e3dd5,0x3de2bd71,0xbde73d5b,0xbddc3d84,0x3dd53d8e,0x3da2bdc6,0xbdac3dbe,0xbd983dce,0x3dfb3cc8,0x3d15bdf5,0xbd2c3df1,0xbcf93df8,
0xbd153df5,0xbc963dfd,0xbc173dff,0xbce03dfa,0xbd8e3dd5,0xbdac3dbe,0xbd9d3dca,0xbdb93db1,0xbded3d44,0xbdf83cf9,0xbdf33d21,0xbdfc3caf,0xbdfbbcc8,0xbdf1bd2c,0xbdf7bd09,0xbdeabd4f,
0xbda23dc6,0xbd2c3df1,0xbcaf3dfc,0xbd7c3ddf,0xbdfb3cc8,0xbdfdbc96,0xbe003b49,0xbdf3bd21,0xbd44bded,0xbbc9be00,0xbce0bdfa,0x3c7bbdfe,0x3dd5bd8e,0x3df8bcf9,0x3deabd4f,0x3dffbc17,
0xbde23d71,0xbd843ddc,0xbd093df7,0xbdb93db1,0xbdd5bd8e,0xbd5bbde7,0xbda7bdc2,0xbcafbdfc,0x3dedbd44,0x3dfd3c96,0x3dfebc7b,0x3dea3d4f,0xbcc83dfb,0xbdac3dbe,0xbd663de5,0xbdd83d89,
0xbdff3c49,0xbdac3dbe,0xbd383def,0xbde53d66,0xbcc8bdfb,0x3d84bddc,0x3cafbdfc,0x3dcabd9d,0x3d443ded,0xbd2c3df1,0x3b493e00,0xbda73dc2,0xbd8ebdd5,0x3c96bdfd,0xbce0bdfa,0x3d7cbddf,
0xbdf5bd15,0xbdce3d98,0xbd663de5,0xbdfc3caf,0x3d8ebdd5,0x3e00bbc9,0x3ddfbd7c,0x3dea3d4f,0xbded3d44,0xbddcbd84,0xbdffbc17,0xbd89bdd8,0x3dfb3cc8,0x3d5b3de7,0x3dca3d9d,0xbb493e00,
0xbdc6bda2,0xbde73d5b,0xbd893dd8,0xbdfebc7b,0x3dfbbcc8,0x3d983dce,0x3def3d38,0x3c173dff,0xbd44bded,0x3dacbdbe,0x3cafbdfc,0x3df7bd09,0xbdd53d8e,0xbddcbd84,0xbe003b49,0xbd66bde5,
0xbd71bde2,0xbdf83cf9,0xbd9d3dca,0xbdeabd4f,0x3dd53d8e,0xbd2c3df1,0x3d213df3,0xbdd83d89,0x3dedbd44,0x3d983dce,0x3df73d09,0xbb493e00,0x3cc8bdfb,0x3e00bbc9,0x3dc2bda7,0x3dd13d93,
0xbc49bdff,0xbe003bc9,0xbdb13db9,0xbdc2bda7,0x3cc83dfb,0xbdf83cf9,0xbd893dd8,0xbddfbd7c,0x3d443ded,0xbde73d5b,0xbd383def,0xbdf3bd21,0x3d8e3dd5,0xbdce3d98,0xbcaf3dfc,0xbdfebc7b,
0x3d15bdf5,0xbdfdbc96,0xbdc23da7,0xbd89bdd8,0xbd8e3dd5,0xbdbebdac,0xbdfe3c7b,0x3b49be00,0xbded3d44,0xbcf9bdf8,0xbde5bd66,0x3d93bdd1,0xbdfbbcc8,0x3d2cbdf1,0xbd7cbddf,0x3defbd38,
0x3da2bdc6,0xbdf1bd2c,0xbdd13d93,0xbd09bdf7,0xbdfb3cc8,0x3c96bdfd,0xbdb9bdb1,0x3de5bd66,0xbd44bded,0x3e00bbc9,0x3d89bdd8,0x3d9d3dca,0x3dd5bd8e,0x3cf93df8,0x3def3d38,0xbda73dc2,
0x3de2bd71,0xbddcbd84,0xbddf3d7c,0x3b49be00,0xbdd5bd8e,0x3de7bd5b,0x3c17bdff,0x3dd13d93,0x3dedbd44,0xbc963dfd,0x3dca3d9d,0xbdef3d38,0xbcc83dfb,0xbdbebdac,0xbdf33d21,0x3ce0bdfa,
0x3dffbc49,0xbdbebdac,0xbdea3d4f,0x3d21bdf3,0xbcc8bdfb,0x3ddc3d84,0x3dd1bd93,0xbc7b3dfe,0x3d443ded,0xbdf1bd2c,0xbdb13db9,0xbc17bdff,0xbd8ebdd5,0x3dfd3c96,0x3d89bdd8,0x3d093df7,
0x3df53d15,0xbd98bdce,0xbdf33d21,0x3d93bdd1,0x3d8ebdd5,0x3bc93e00,0x3df73d09,0xbdef3d38,0xbded3d44,0x3d84bddc,0xbda7bdc2,0x3dfa3ce0,0x3dfb3cc8,0xbde73d5b,0x3c7b3dfe,0xbdb1bdb9,
0x3dc63da2,0xbd5bbde7,0xbdfa3ce0,0x3dcabd9d,0x3dfbbcc8,0xbdce3d98,0x3d4f3dea,0xbdc2bda7,0xbd44bded,0x3dbe3dac,0x3dd1bd93,0xbd7c3ddf,0xbdd53d8e,0x3d84bddc,0xbdb9bdb1,0x3df33d21,
0x3d713de2,0xbcf9bdf8,0xbdfe3c7b,0x3defbd38,0x3dd53d8e,0xbdf1bd2c,0xbd663de5,0x3ce0bdfa,0x3dedbd44,0xbdce3d98,0x3d7c3ddf,0xbdb1bdb9,0x3cc8bdfb,0x3bc93e00,0x3dff3c17,0xbdfc3caf,
0x3c493dff,0xbbc9be00,0xbe003b49,0x3dffbc17,0x3cc83dfb,0xbcf9bdf8,0xbdfa3ce0,0x3df7bd09,0x3d443ded,0xbd5bbde7,0xbdea3d4f,0x3de5bd66,0x3d8e3dd5,0xbd98bdce,0xbdd13d93,0x3dcabd9d,
0xbd153df5,0x3c96bdfd,0xbdffbc17,0x3dfa3ce0,0xbd8e3dd5,0x3dacbdbe,0xbdcabd9d,0x3db13db9,0xbded3d44,0x3df8bcf9,0xbd21bdf3,0x3caf3dfc,0xbdfbbcc8,0x3df13d2c,0x3d09bdf7,0xbd4f3dea,
0xbda23dc6,0x3d2cbdf1,0xbdfcbcaf,0x3ddf3d7c,0xbdfb3cc8,0x3dfd3c96,0xbb49be00,0xbd213df3,0xbd44bded,0x3bc93e00,0x3dfabce0,0xbdfebc7b,0x3dd5bd8e,0xbdf83cf9,0x3d4f3dea,0xbc17bdff,
0xbde23d71,0x3d84bddc,0xbdf7bd09,0x3db13db9,0xbdd5bd8e,0x3d5b3de7,0x3dc2bda7,0xbdfc3caf,0x3dedbd44,0xbdfdbc96,0x3c7b3dfe,0x3d4fbdea,0xbcc83dfb,0x3dacbdbe,0xbde5bd66,0x3d893dd8,
0xbdff3c49,0x3dacbdbe,0xbdefbd38,0x3d663de5,0xbcc8bdfb,0xbd843ddc,0x3dfc3caf,0xbd9dbdca,0x3d443ded,0x3d2cbdf1,0xbe003b49,0x3dc23da7,0xbd8ebdd5,0xbc963dfd,0x3dfabce0,0xbddfbd7c,
0xbdf5bd15,0x3dcebd98,0xbde5bd66,0x3caf3dfc,0x3d8ebdd5,0xbe003bc9,0x3d7c3ddf,0x3d4fbdea,0xbded3d44,0x3ddc3d84,0x3c17bdff,0xbdd83d89,0x3dfb3cc8,0xbd5bbde7,0xbd9d3dca,0x3e003b49,
0xbdc6bda2,0x3de7bd5b,0xbdd8bd89,0xbc7b3dfe,0x3dfbbcc8,0xbd98bdce,0xbd383def,0x3dffbc17,0xbd44bded,0xbdac3dbe,0x3dfc3caf,0xbd09bdf7,0xbdd53d8e,0x3ddc3d84,0xbb49be00,0xbde53d66,
0xbd71bde2,0x3df8bcf9,0xbdcabd9d,0xbd4f3dea,0x3dd53d8e,0x3d2cbdf1,0xbdf33d21,0x3d893dd8,0x3dedbd44,0xbd98bdce,0xbd093df7,0x3e003b49,0x3cc8bdfb,0xbe003bc9,0x3da73dc2,0x3d93bdd1,
0xbc49bdff,0x3e00bbc9,0xbdb9bdb1,0xbda73dc2,0x3cc83dfb,0x3df8bcf9,0xbdd8bd89,0xbd7c3ddf,0x3d443ded,0x3de7bd5b,0xbdefbd38,0xbd213df3,0x3d8e3dd5,0x3dcebd98,0xbdfcbcaf,0xbc7b3dfe,
0x3d15bdf5,0x3dfd3c96,0xbda7bdc2,0xbdd83d89,0xbd8e3dd5,0x3dbe3dac,0xbc7bbdfe,0xbe00bb49,0xbded3d44,0x3cf93df8,0x3d66bde5,0xbdd1bd93,0xbdfbbcc8,0xbd2c3df1,0x3ddfbd7c,0xbd38bdef,
0x3da2bdc6,0x3df13d2c,0xbd93bdd1,0xbdf73d09,0xbdfb3cc8,0xbc963dfd,0x3db1bdb9,0xbd66bde5,0xbd44bded,0xbe003bc9,0x3dd83d89,0x3dcabd9d,0x3dd5bd8e,0xbcf9bdf8,0xbd383def,0x3dc23da7,
0x3de2bd71,0x3ddc3d84,0xbd7cbddf,0xbe00bb49,0xbdd5bd8e,0xbde73d5b,0x3dff3c17,0x3d93bdd1,0x3dedbd44,0x3c96bdfd,0xbd9d3dca,0x3d383def,0xbcc83dfb,0x3dbe3dac,0xbd21bdf3,0xbdfabce0,
0x3dffbc49,0x3dbe3dac,0xbd4fbdea,0xbdf3bd21,0xbcc8bdfb,0xbddcbd84,0x3d933dd1,0x3dfe3c7b,0x3d443ded,0x3df13d2c,0xbdb9bdb1,0xbdff3c17,0xbd8ebdd5,0xbdfdbc96,0x3dd83d89,0x3df7bd09,
0x3df53d15,0x3d983dce,0xbd21bdf3,0xbdd1bd93,0x3d8ebdd5,0xbbc9be00,0xbd093df7,0x3d383def,0xbded3d44,0xbd843ddc,0x3dc2bda7,0x3ce0bdfa,0x3dfb3cc8,0x3de7bd5b,0xbdfe3c7b,0xbdb93db1,
0x3dc63da2,0x3d5b3de7,0xbce0bdfa,0xbd9dbdca,0x3dfbbcc8,0x3dcebd98,0xbdea3d4f,0xbda73dc2,0xbd44bded,0xbdbebdac,0x3d933dd1,0x3ddf3d7c,0xbdd53d8e,0xbd843ddc,0x3db1bdb9,0x3d21bdf3,
0x3d713de2,0x3cf93df8,0xbc7bbdfe,0xbd38bdef,0x3dd53d8e,0x3df13d2c,0xbde5bd66,0xbdfabce0,0x3dedbd44,0x3dcebd98,0xbddf3d7c,0xbdb93db1,0x3cc8bdfb,0xbbc9be00,0xbc173dff,0x3caf3dfc,
0x3c493dff,0x3bc93e00,0xbb49be00,0xbc17bdff,0x3cc83dfb,0x3cf93df8,0xbce0bdfa,0xbd09bdf7,0x3d443ded,0x3d5b3de7,0xbd4fbdea,0xbd66bde5,0x3d8e3dd5,0x3d983dce,0xbd93bdd1,0xbd9dbdca,
0xbdb53d80,0xbd98bdce,0xbda7bdc2,0xbd89bdd8,0xbdc63da2,0xbbc9be00,0xbc7bbdfe,0x3b49be00,0xbdff3c49,0x3d84bddc,0x3d66bde5,0x3d93bdd1,0xbde2bd71,0x3de7bd5b,0x3ddfbd7c,0x3defbd38,
0x3db53d80,0x3d5b3de7,0x3d933dd1,0x3d093df7,0xbde2bd71,0xbdce3d98,0xbdb13db9,0xbde53d66,0x3d15bdf5,0xbdbebdac,0xbdd8bd89,0xbd9dbdca,0x3dff3c49,0x3d84bddc,0x3d38bdef,0x3da7bdc2,
0xbdb53d80,0xbcf9bdf8,0xbd7cbddf,0x3b49be00,0x3c49bdff,0x3df13d2c,0x3dff3c17,0x3dd13d93,0x3dc63da2,0xbdce3d98,0xbd9d3dca,0xbdef3d38,0xbdf53d15,0xbbc9be00,0xbd21bdf3,0x3ce0bdfa,
0x3db53d80,0x3bc93e00,0x3d4f3dea,0xbd213df3,0x3df5bd15,0xbcf9bdf8,0xbd93bdd1,0x3c7bbdfe,0xbde23d71,0x3d5b3de7,0x3db93db1,0x3c173dff,0x3dc6bda2,0xbd98bdce,0xbdd8bd89,0xbd09bdf7,
0xbdb53d80,0x3c96bdfd,0xbd21bdf3,0x3d93bdd1,0x3da23dc6,0xbdac3dbe,0xbd093df7,0xbdef3d38,0xbc49bdff,0x3df8bcf9,0x3dc2bda7,0x3dfa3ce0,0xbd713de2,0xbdf1bd2c,0xbdfe3c7b,0xbdb1bdb9,
0x3db53d80,0xbd2c3df1,0x3ce03dfa,0xbdca3d9d,0xbd713de2,0x3dfd3c96,0x3deabd4f,0x3dc23da7,0x3df53d15,0xbbc9be00,0xbd93bdd1,0x3d7cbddf,0x3c49bdff,0xbdf83cf9,0xbdb13db9,0xbdf3bd21,
0xbdb53d80,0x3d84bddc,0xbc7bbdfe,0x3defbd38,0xbdffbc49,0xbd5bbde7,0xbde5bd66,0x3ce0bdfa,0xbda23dc6,0xbdfdbc96,0xbddf3d7c,0xbdb1bdb9,0x3d153df5,0xbdac3dbe,0xbc173dff,0xbdfc3caf,
0x3db53d80,0xbdac3dbe,0x3b493e00,0xbdff3c17,0xbd15bdf5,0xbd843ddc,0x3ce03dfa,0xbdf73d09,0xbd71bde2,0xbd2c3df1,0x3d4f3dea,0xbde53d66,0xbda2bdc6,0xbc963dfd,0x3d933dd1,0xbdca3d9d,
0xbdb53d80,0x3dcebd98,0x3c17bdff,0x3dfa3ce0,0x3dc6bda2,0x3e00bbc9,0x3d9dbdca,0x3db13db9,0x3dffbc49,0x3ddc3d84,0x3df3bd21,0x3caf3dfc,0x3de23d71,0x3d5b3de7,0x3df73d09,0xbd4f3dea,
0x3db53d80,0xbde73d5b,0xbcaf3dfc,0xbddfbd7c,0x3de23d71,0xbd98bdce,0xbe003b49,0x3d21bdf3,0xbd153df5,0x3dacbdbe,0xbce0bdfa,0x3dfe3c7b,0xbdffbc49,0x3ddc3d84,0x3deabd4f,0x3c173dff,
0xbdb53d80,0x3df8bcf9,0x3d09bdf7,0x3db13db9,0xbc493dff,0xbd2c3df1,0x3da73dc2,0xbdfc3caf,0xbdc6bda2,0xbd98bdce,0xbdfe3c7b,0x3d4fbdea,0x3df5bd15,0x3e00bbc9,0x3d66bde5,0x3d893dd8,
0x3db53d80,0xbe003bc9,0xbd383def,0xbd66bde5,0xbdf53d15,0x3df8bcf9,0x3cafbdfc,0x3d9d3dca,0x3de2bd71,0xbde73d5b,0x3b493e00,0xbdc2bda7,0xbdc63da2,0x3dcebd98,0xbce0bdfa,0x3ddf3d7c,
0xbdb53d80,0x3dfd3c96,0x3d66bde5,0x3caf3dfc,0xbda2bdc6,0xbdbebdac,0xbddf3d7c,0x3d4fbdea,0x3c493dff,0x3cf93df8,0x3dff3c17,0xbdd83d89,0x3d71bde2,0x3d2cbdf1,0xbdcabd9d,0x3e003b49,
0x3db53d80,0xbdf1bd2c,0xbd893dd8,0x3c7bbdfe,0x3d71bde2,0xbc963dfd,0x3def3d38,0xbdff3c17,0xbdf5bd15,0x3e00bbc9,0x3cafbdfc,0x3d093df7,0xbc493dff,0xbcf9bdf8,0xbe003b49,0x3de5bd66,
0xbdb53d80,0x3ddc3d84,0x3d9dbdca,0xbd4f3dea,0x3dff3c49,0x3de7bd5b,0xbd21bdf3,0x3d893dd8,0x3da2bdc6,0x3c96bdfd,0xbdf7bd09,0x3e003b49,0xbd15bdf5,0xbdbebdac,0xbdc23da7,0x3d93bdd1,
0x3db53d80,0xbdbebdac,0xbdb13db9,0x3da7bdc2,0x3d153df5,0xbddcbd84,0xbd893dd8,0x3d7cbddf,0x3d713de2,0xbdf1bd2c,0xbd383def,0x3d21bdf3,0x3da23dc6,0xbdfdbc96,0xbcaf3dfc,0x3c7bbdfe,
0xbdb53d80,0x3d983dce,0x3dc2bda7,0xbdd83d89,0xbdc63da2,0x3bc93e00,0x3dfebc7b,0xbe00bb49,0xbdff3c49,0xbd843ddc,0x3de53d66,0xbdd1bd93,0xbde2bd71,0xbde73d5b,0x3d7c3ddf,0xbd38bdef,
0x3db53d80,0xbd5bbde7,0xbdd13d93,0x3df7bd09,0xbde2bd71,0x3dcebd98,0xbdb9bdb1,0x3d663de5,0x3d15bdf5,0x3dbe3dac,0x3d89bdd8,0xbdca3d9d,0x3dff3c49,0xbd843ddc,0x3def3d38,0xbdc2bda7,
0xbdb53d80,0x3cf93df8,0x3ddfbd7c,0xbe00bb49,0x3c49bdff,0xbdf1bd2c,0xbc173dff,0x3d93bdd1,0x3dc63da2,0x3dcebd98,0xbdcabd9d,0x3d383def,0xbdf53d15,0x3bc93e00,0x3df3bd21,0xbdfabce0,
0x3db53d80,0xbbc9be00,0xbdea3d4f,0x3df33d21,0x3df5bd15,0x3cf93df8,0x3dd1bd93,0xbdfebc7b,0xbde23d71,0xbd5bbde7,0xbdb13db9,0x3dffbc17,0x3dc6bda2,0x3d983dce,0x3d89bdd8,0xbdf73d09,
0xbdb53d80,0xbc963dfd,0x3df3bd21,0xbdd1bd93,0x3da23dc6,0x3dacbdbe,0xbdf7bd09,0x3d383def,0xbc49bdff,0xbdf83cf9,0x3da73dc2,0x3ce0bdfa,0xbd713de2,0x3df13d2c,0xbc7bbdfe,0xbdb93db1,
0x3db53d80,0x3d2cbdf1,0xbdfa3ce0,0x3d9d3dca,0xbd713de2,0xbdfdbc96,0x3d4f3dea,0x3da7bdc2,0x3df53d15,0x3bc93e00,0x3dd1bd93,0xbddfbd7c,0x3c49bdff,0x3df8bcf9,0xbdb9bdb1,0xbd213df3,
0xbdb53d80,0xbd843ddc,0x3dfebc7b,0xbd38bdef,0xbdffbc49,0x3d5b3de7,0x3d66bde5,0xbdfabce0,0xbda23dc6,0x3dfd3c96,0xbd7cbddf,0xbdb93db1,0x3d153df5,0x3dacbdbe,0xbdffbc17,0x3caf3dfc,
0x3db53d80,0x3dacbdbe,0xbe003b49,0x3c173dff,0xbd15bdf5,0x3d84bddc,0xbdfa3ce0,0x3d093df7,0xbd71bde2,0x3d2cbdf1,0xbdea3d4f,0x3d663de5,0xbda2bdc6,0x3c96bdfd,0xbdd13d93,0x3d9d3dca,
0xbdb53d80,0xbdce3d98,0x3dff3c17,0x3ce0bdfa,0x3dc6bda2,0xbe003bc9,0x3dca3d9d,0x3db9bdb1,0x3dffbc49,0xbddcbd84,0x3d213df3,0x3dfcbcaf,0x3de23d71,0xbd5bbde7,0xbd093df7,0x3dea3d4f,
0x3db53d80,0x3de7bd5b,0xbdfcbcaf,0xbd7c3ddf,0x3de23d71,0x3d983dce,0xbb49be00,0xbdf3bd21,0xbd153df5,0xbdac3dbe,0x3dfabce0,0x3c7bbdfe,0xbdffbc49,0xbddcbd84,0x3d4f3dea,0x3dffbc17,
0xbdb53d80,0xbdf83cf9,0x3df73d09,0x3db9bdb1,0xbc493dff,0x3d2cbdf1,0xbdc23da7,0x3caf3dfc,0xbdc6bda2,0x3d983dce,0xbc7bbdfe,0xbdeabd4f,0x3df5bd15,0xbe003bc9,0x3de53d66,0x3dd8bd89,
0x3db53d80,0x3e00bbc9,0xbdefbd38,0xbde53d66,0xbdf53d15,0xbdf83cf9,0x3dfc3caf,0x3dcabd9d,0x3de2bd71,0x3de7bd5b,0xbe003b49,0xbda73dc2,0xbdc63da2,0xbdce3d98,0x3dfabce0,0x3d7cbddf,
0xbdb53d80,0xbdfdbc96,0x3de53d66,0x3dfcbcaf,0xbda2bdc6,0x3dbe3dac,0xbd7cbddf,0xbdeabd4f,0x3c493dff,0xbcf9bdf8,0xbc173dff,0x3d893dd8,0x3d71bde2,0xbd2c3df1,0x3d9dbdca,0x3b49be00,
0x3db53d80,0x3df13d2c,0xbdd8bd89,0xbdfebc7b,0x3d71bde2,0x3c96bdfd,0xbd383def,0x3c173dff,0xbdf5bd15,0xbe003bc9,0x3dfc3caf,0x3df7bd09,0xbc493dff,0x3cf93df8,0xbb49be00,0xbd66bde5,
0xbdb53d80,0xbddcbd84,0x3dca3d9d,0x3dea3d4f,0x3dff3c49,0xbde73d5b,0x3df3bd21,0x3dd8bd89,0x3da2bdc6,0xbc963dfd,0x3d09bdf7,0x3b49be00,0xbd15bdf5,0x3dbe3dac,0xbda7bdc2,0xbdd1bd93,
0x3db53d80,0x3dbe3dac,0xbdb9bdb1,0xbdc2bda7,0x3d153df5,0x3ddc3d84,0xbdd8bd89,0xbddfbd7c,0x3d713de2,0x3df13d2c,0xbdefbd38,0xbdf3bd21,0x3da23dc6,0x3dfd3c96,0xbdfcbcaf,0xbdfebc7b,
0x3f800000,0x0,0x3f800000,0x0,0x3f800000,0x0,0x3f800000,0x0,0x3f800000,0x0,0x3f800000,0x0,0x3f800000,0x0,0x3f800000,0x0,
0x3f800000,0x0,0x3f7ffb11,0xbc490e90,0x3f7fec43,0xbcc90ab0,0x3f7fd397,0xbd16c32c,0x3f7fb10f,0xbd48fb30,0x3f7f84ab,0xbd7b2b74,0x3f7f4e6d,0xbd96a905,0x3f7f0e58,0xbdafb680,
0x3f800000,0x0,0x3f7fec43,0xbcc90ab0,0x3f7fb10f,0xbd48fb30,0x3f7f4e6d,0xbd96a905,0x3f7ec46d,0xbdc8bd36,0x3f7e1324,0xbdfab273,0x3f7d3aac,0xbe164083,0x3f7c3b28,0xbe2f10a2,
0x3f800000,0x0,0x3f7fd397,0xbd16c32c,0x3f7f4e6d,0xbd96a905,0x3f7e70b0,0xbde1bc2e,0x3f7d3aac,0xbe164083,0x3f7baccd,0xbe3b6ecf,0x3f79c79d,0xbe605c13,0x3f778bc5,0xbe827dc0,
0x3f800000,0x0,0x3f7fb10f,0xbd48fb30,0x3f7ec46d,0xbdc8bd36,0x3f7d3aac,0xbe164083,0x3f7b14be,0xbe47c5c2,0x3f7853f8,0xbe78cfcc,0x3f74fa0b,0xbe94a031,0x3f710908,0xbeac7cd4,
0x3f800000,0x0,0x3f7f84ab,0xbd7b2b74,0x3f7e1324,0xbdfab273,0x3f7baccd,0xbe3b6ecf,0x3f7853f8,0xbe78cfcc,0x3f740bdd,0xbe9aa086,0x3f6ed89e,0xbeb8442a,0x3f68bf3c,0xbed53641,
0x3f800000,0x0,0x3f7f4e6d,0xbd96a905,0x3f7d3aac,0xbe164083,0x3f79c79d,0xbe605c13,0x3f74fa0b,0xbe94a031,0x3f6ed89e,0xbeb8442a,0x3f676bd8,0xbedae880,0x3f5ebe05,0xbefc5d27,
0x3f800000,0x0,0x3f7f0e58,0xbdafb680,0x3f7c3b28,0xbe2f10a2,0x3f778bc5,0xbe827dc0,0x3f710908,0xbeac7cd4,0x3f68bf3c,0xbed53641,0x3f5ebe05,0xbefc5d27,0x3f531849,0xbf10d3cd,
0x3f800000,0x0,0x3f7b14be,0xbe47c5c2,0x3f6c835e,0xbec3ef15,0x3f54db31,0xbf0e39da,0x3f3504f3,0xbf3504f3,0x3f0e39da,0xbf54db31,0x3ec3ef15,0xbf6c835e,0x3e47c5c2,0xbf7b14be,
0x3f800000,0x0,0x3f7a7302,0xbe541501,0x3f6a09a7,0xbecf7bca,0x3f4f7a1f,0xbf15f6d9,0x3f2beb4a,0xbf3daef9,0x3f00e7e4,0xbf5d2d53,0x3ea09ae5,0xbf731447,0x3de1bc2e,0xbf7e70b0,
0x3f800000,0x0,0x3f79c79d,0xbe605c13,0x3f676bd8,0xbedae880,0x3f49d112,0xbf1d7fd1,0x3f226799,0xbf45e403,0x3ee63375,0xbf64aa59,0x3e78cfcc,0xbf7853f8,0x3cc90ab0,0xbf7fec43,
0x3f800000,0x0,0x3f791298,0xbe6c9a7f,0x3f64aa59,0xbee63375,0x3f43e200,0xbf24d225,0x3f187fc0,0xbf4d9f02,0x3ec9b953,0xbf6b4b0c,0x3e2f10a2,0xbf7c3b28,0xbd7b2b74,0xbf7f84ab,
0x3f800000,0x0,0x3f7853f8,0xbe78cfcc,0x3f61c598,0xbef15aea,0x3f3daef9,0xbf2beb4a,0x3f0e39da,0xbf54db31,0x3eac7cd4,0xbf710908,0x3dc8bd36,0xbf7ec46d,0xbe164083,0xbf7d3aac,
0x3f800000,0x0,0x3f778bc5,0xbe827dc0,0x3f5ebe05,0xbefc5d27,0x3f373a23,0xbf32c8c9,0x3f039c3d,0xbf5b941a,0x3e8e9a22,0xbf75dec6,0x3cc90ab0,0xbf7fec43,0xbe6c9a7f,0xbf791298,
0x3f800000,0x0,0x3f76ba07,0xbe888e93,0x3f5b941a,0xbf039c3d,0x3f3085bb,0xbf396842,0x3ef15aea,0xbf61c598,0x3e605c13,0xbf79c79d,0xbd48fb30,0xbf7fb10f,0xbea09ae5,0xbf731447,
0x3f800000,0x0,0x3f75dec6,0xbe8e9a22,0x3f584853,0xbf08f59b,0x3f299415,0xbf3fc767,0x3edae880,0xbf676bd8,0x3e22abb6,0xbf7cbfc9,0xbdfab273,0xbf7e1324,0xbec9b953,0xbf6b4b0c,
0x3f800000,0x0,0x3f7ec46d,0xbdc8bd36,0x3f7b14be,0xbe47c5c2,0x3f74fa0b,0xbe94a031,0x3f6c835e,0xbec3ef15,0x3f61c598,0xbef15aea,0x3f54db31,0xbf0e39da,0x3f45e403,0xbf226799,
0x3f800000,0x0,0x3f6b4b0c,0xbec9b953,0x3f3085bb,0xbf396842,0x3eb263ef,0xbf6ff573,0xbd48fb30,0xbf7fb10f,0xbee0924f,0xbf660f88,0xbf41d870,0xbf273656,0xbf740bdd,0xbe9aa086,
0x3f800000,0x0,0x3f6a09a7,0xbecf7bca,0x3f2beb4a,0xbf3daef9,0x3ea09ae5,0xbf731447,0xbdc8bd36,0xbf7ec46d,0xbefc5d27,0xbf5ebe05,0xbf4d9f02,0xbf187fc0,0xbf79c79d,0xbe605c13,
0x3f800000,0x0,0x3f68bf3c,0xbed53641,0x3f273656,0xbf41d870,0x3e8e9a22,0xbf75dec6,0xbe164083,0xbf7d3aac,0xbf0b9a6b,0xbf5695e5,0xbf584853,0xbf08f59b,0xbf7dabcc,0xbe09cf86,
0x3f800000,0x0,0x3f676bd8,0xbedae880,0x3f226799,0xbf45e403,0x3e78cfcc,0xbf7853f8,0xbe47c5c2,0xbf7b14be,0xbf187fc0,0xbf4d9f02,0xbf61c598,0xbef15aea,0xbf7fb10f,0xbd48fb30,
0x3f800000,0x0,0x3f660f88,0xbee0924f,0x3f1d7fd1,0xbf49d112,0x3e541501,0xbf7a7302,0xbe78cfcc,0xbf7853f8,0xbf24d225,0xbf43e200,0xbf6a09a7,0xbecf7bca,0xbf7fd397,0x3d16c32c,
0x3f800000,0x0,0x3f64aa59,0xbee63375,0x3f187fc0,0xbf4d9f02,0x3e2f10a2,0xbf7c3b28,0xbe94a031,0xbf74fa0b,0xbf3085bb,0xbf396842,0xbf710908,0xbeac7cd4,0xbf7e1324,0x3dfab273,
0x3f800000,0x0,0x3f633c5a,0xbeebcbbb,0x3f13682a,0xbf514d3d,0x3e09cf86,0xbf7dabcc,0xbeac7cd4,0xbf710908,0xbf3b8f3b,0xbf2e3bde,0xbf76ba07,0xbe888e93,0xbf7a7302,0x3e541501,
0x3f800000,0x0,0x3f74fa0b,0xbe94a031,0x3f54db31,0xbf0e39da,0x3f226799,0xbf45e403,0x3ec3ef15,0xbf6c835e,0x3dc8bd36,0xbf7ec46d,0xbe47c5c2,0xbf7b14be,0xbef15aea,0xbf61c598,
0x3f800000,0x0,0x3f531849,0xbf10d3cd,0x3eb8442a,0xbf6ed89e,0xbe6c9a7f,0xbf791298,0xbf3daef9,0xbf2beb4a,0xbf7dabcc,0xbe09cf86,0xbf64aa59,0x3ee63375,0xbef6e0cb,0x3f604621,
0x3f800000,0x0,0x3f514d3d,0xbf13682a,0x3eac7cd4,0xbf710908,0xbe888e93,0xbf76ba07,0xbf45e403,0xbf226799,0xbf7f4e6d,0xbd96a905,0xbf5b941a,0x3f039c3d,0xbecf7bca,0x3f6a09a7,
0x3f800000,0x0,0x3f4f7a1f,0xbf15f6d9,0x3ea09ae5,0xbf731447,0xbe9aa086,0xbf740bdd,0xbf4d9f02,0xbf187fc0,0xbf7ffb11,0xbc490e90,0xbf514d3d,0x3f13682a,0xbea68f12,0x3f721352,
0x3f800000,0x0,0x3f4d9f02,0xbf187fc0,0x3e94a031,0xbf74fa0b,0xbeac7cd4,0xbf710908,0xbf54db31,0xbf0e39da,0xbf7fb10f,0x3d48fb30,0xbf45e403,0x3f226799,0xbe78cfcc,0x3f7853f8,
0x3f800000,0x0,0x3f4bbbf8,0xbf1b02c6,0x3e888e93,0xbf76ba07,0xbebe1d4a,0xbf6db293,0xbf5b941a,0xbf039c3d,0xbf7e70b0,0x3de1bc2e,0xbf396842,0x3f3085bb,0xbe22abb6,0x3f7cbfc9,
0x3f800000,0x0,0x3f49d112,0xbf1d7fd1,0x3e78cfcc,0xbf7853f8,0xbecf7bca,0xbf6a09a7,0xbf61c598,0xbef15aea,0xbf7c3b28,0x3e2f10a2,0xbf2beb4a,0x3f3daef9,0xbd96a905,0x3f7f4e6d,
0x3f800000,0x0,0x3f47de65,0xbf1ff6cb,0x3e605c13,0xbf79c79d,0xbee0924f,0xbf660f88,0xbf676bd8,0xbedae880,0xbf791298,0x3e6c9a7f,0xbf1d7fd1,0x3f49d112,0x3c490e90,0x3f7ffb11,
0x3f800000,0x0,0x3f800000,0x0,0x3f800000,0x0,0x3f800000,0x0,0x40000000,0x0,0x3f800000,0x0,0x3f800000,0x0,0x3f800000,0x0,
0x3f800000,0x0,0x3f7ffb11,0xbc490e90,0x3f7fec43,0xbcc90ab0,0x3f7fd397,0xbd16c32c,0x3fffb10f,0xbdc8fb30,0x3f7f84ab,0xbd7b2b74,0x3f7f4e6d,0xbd96a905,0x3f7f0e58,0xbdafb680,
0x3f800000,0x0,0x3f7fec43,0xbcc90ab0,0x3f7fb10f,0xbd48fb30,0x3f7f4e6d,0xbd96a905,0x3ffec46d,0xbe48bd36,0x3f7e1324,0xbdfab273,0x3f7d3aac,0xbe164083,0x3f7c3b28,0xbe2f10a2,
0x3f800000,0x0,0x3f7fd397,0xbd16c32c,0x3f7f4e6d,0xbd96a905,0x3f7e70b0,0xbde1bc2e,0x3ffd3aac,0xbe964083,0x3f7baccd,0xbe3b6ecf,0x3f79c79d,0xbe605c13,0x3f778bc5,0xbe827dc0,
0x3f800000,0x0,0x3f7fb10f,0xbd48fb30,0x3f7ec46d,0xbdc8bd36,0x3f7d3aac,0xbe164083,0x3ffb14be,0xbec7c5c2,0x3f7853f8,0xbe78cfcc,0x3f74fa0b,0xbe94a031,0x3f710908,0xbeac7cd4,
0x3f800000,0x0,0x3f7f84ab,0xbd7b2b74,0x3f7e1324,0xbdfab273,0x3f7baccd,0xbe3b6ecf,0x3ff853f8,0xbef8cfcc,0x3f740bdd,0xbe9aa086,0x3f6ed89e,0xbeb8442a,0x3f68bf3c,0xbed53641,
0x3f800000,0x0,0x3f7f4e6d,0xbd96a905,0x3f7d3aac,0xbe164083,0x3f79c79d,0xbe605c13,0x3ff4fa0b,0xbf14a031,0x3f6ed89e,0xbeb8442a,0x3f676bd8,0xbedae880,0x3f5ebe05,0xbefc5d27,
0x3f800000,0x0,0x3f7f0e58,0xbdafb680,0x3f7c3b28,0xbe2f10a2,0x3f778bc5,0xbe827dc0,0x3ff10908,0xbf2c7cd4,0x3f68bf3c,0xbed53641,0x3f5ebe05,0xbefc5d27,0x3f531849,0xbf10d3cd,
0x3f800000,0x0,0x3f7ec46d,0xbdc8bd36,0x3f7b14be,0xbe47c5c2,0x3f74fa0b,0xbe94a031,0x3fec835e,0xbf43ef15,0x3f61c598,0xbef15aea,0x3f54db31,0xbf0e39da,0x3f45e403,0xbf226799,
0x3f800000,0x0,0x3f7e70b0,0xbde1bc2e,0x3f79c79d,0xbe605c13,0x3f721352,0xbea68f12,0x3fe76bd8,0xbf5ae880,0x3f59f26a,0xbf064b82,0x3f49d112,0xbf1d7fd1,0x3f373a23,0xbf32c8c9,
0x3f800000,0x0,0x3f7e1324,0xbdfab273,0x3f7853f8,0xbe78cfcc,0x3f6ed89e,0xbeb8442a,0x3fe1c598,0xbf715aea,0x3f514d3d,0xbf13682a,0x3f3daef9,0xbf2beb4a,0x3f273656,0xbf41d870,
0x3f800000,0x0,0x3f7dabcc,0xbe09cf86,0x3f76ba07,0xbe888e93,0x3f6b4b0c,0xbec9b953,0x3fdb941a,0xbf839c3d,0x3f47de65,0xbf1ff6cb,0x3f3085bb,0xbf396842,0x3f15f6d9,0xbf4f7a1f,
0x3f800000,0x0,0x3f7d3aac,0xbe164083,0x3f74fa0b,0xbe94a031,0x3f676bd8,0xbedae880,0x3fd4db31,0xbf8e39da,0x3f3daef9,0xbf2beb4a,0x3f226799,0xbf45e403,0x3f039c3d,0xbf5b941a,
0x3f800000,0x0,0x3f7cbfc9,0xbe22abb6,0x3f731447,0xbea09ae5,0x3f633c5a,0xbeebcbbb,0x3fcd9f02,0xbf987fc0,0x3f32c8c9,0xbf373a23,0x3f13682a,0xbf514d3d,0x3ee0924f,0xbf660f88,
0x3f800000,0x0,0x3f7c3b28,0xbe2f10a2,0x3f710908,0xbeac7cd4,0x3f5ebe05,0xbefc5d27,0x3fc5e403,0xbfa26799,0x3f273656,0xbf41d870,0x3f039c3d,0xbf5b941a,0x3eb8442a,0xbf6ed89e,
0x3f800000,0x0,0x3f7baccd,0xbe3b6ecf,0x3f6ed89e,0xbeb8442a,0x3f59f26a,0xbf064b82,0x3fbdaef9,0xbfabeb4a,0x3f1b02c6,0xbf4bbbf8,0x3ee63375,0xbf64aa59,0x3e8e9a22,0xbf75dec6,
0x3f800000,0x0,0x3f7b14be,0xbe47c5c2,0x3f6c835e,0xbec3ef15,0x3f54db31,0xbf0e39da,0x3fb504f3,0xbfb504f3,0x3f0e39da,0xbf54db31,0x3ec3ef15,0xbf6c835e,0x3e47c5c2,0xbf7b14be,
0x3f800000,0x0,0x3f7a7302,0xbe541501,0x3f6a09a7,0xbecf7bca,0x3f4f7a1f,0xbf15f6d9,0x3fabeb4a,0xbfbdaef9,0x3f00e7e4,0xbf5d2d53,0x3ea09ae5,0xbf731447,0x3de1bc2e,0xbf7e70b0,
0x3f800000,0x0,0x3f79c79d,0xbe605c13,0x3f676bd8,0xbedae880,0x3f49d112,0xbf1d7fd1,0x3fa26799,0xbfc5e403,0x3ee63375,0xbf64aa59,0x3e78cfcc,0xbf7853f8,0x3cc90ab0,0xbf7fec43,
0x3f800000,0x0,0x3f791298,0xbe6c9a7f,0x3f64aa59,0xbee63375,0x3f43e200,0xbf24d225,0x3f987fc0,0xbfcd9f02,0x3ec9b953,0xbf6b4b0c,0x3e2f10a2,0xbf7c3b28,0xbd7b2b74,0xbf7f84ab,
0x3f800000,0x0,0x3f7853f8,0xbe78cfcc,0x3f61c598,0xbef15aea,0x3f3daef9,0xbf2beb4a,0x3f8e39da,0xbfd4db31,0x3eac7cd4,0xbf710908,0x3dc8bd36,0xbf7ec46d,0xbe164083,0xbf7d3aac,
0x3f800000,0x0,0x3f778bc5,0xbe827dc0,0x3f5ebe05,0xbefc5d27,0x3f373a23,0xbf32c8c9,0x3f839c3d,0xbfdb941a,0x3e8e9a22,0xbf75dec6,0x3cc90ab0,0xbf7fec43,0xbe6c9a7f,0xbf791298,
0x3f800000,0x0,0x3f76ba07,0xbe888e93,0x3f5b941a,0xbf039c3d,0x3f3085bb,0xbf396842,0x3f715aea,0xbfe1c598,0x3e605c13,0xbf79c79d,0xbd48fb30,0xbf7fb10f,0xbea09ae5,0xbf731447,
0x3f800000,0x0,0x3f75dec6,0xbe8e9a22,0x3f584853,0xbf08f59b,0x3f299415,0xbf3fc767,0x3f5ae880,0xbfe76bd8,0x3e22abb6,0xbf7cbfc9,0xbdfab273,0xbf7e1324,0xbec9b953,0xbf6b4b0c,
0x3f800000,0x0,0x3f74fa0b,0xbe94a031,0x3f54db31,0xbf0e39da,0x3f226799,0xbf45e403,0x3f43ef15,0xbfec835e,0x3dc8bd36,0xbf7ec46d,0xbe47c5c2,0xbf7b14be,0xbef15aea,0xbf61c598,
0x3f800000,0x0,0x3f740bdd,0xbe9aa086,0x3f514d3d,0xbf13682a,0x3f1b02c6,0xbf4bbbf8,0x3f2c7cd4,0xbff10908,0x3d16c32c,0xbf7fd397,0xbe888e93,0xbf76ba07,0xbf0b9a6b,0xbf5695e5,
0x3f800000,0x0,0x3f731447,0xbea09ae5,0x3f4d9f02,0xbf187fc0,0x3f13682a,0xbf514d3d,0x3f14a031,0xbff4fa0b,0xbcc90ab0,0xbf7fec43,0xbeac7cd4,0xbf710908,0xbf1d7fd1,0xbf49d112,
0x3f800000,0x0,0x3f721352,0xbea68f12,0x3f49d112,0xbf1d7fd1,0x3f0b9a6b,0xbf5695e5,0x3ef8cfcc,0xbff853f8,0xbdafb680,0xbf7f0e58,0xbecf7bca,0xbf6a09a7,0xbf2e3bde,0xbf3b8f3b,
0x3f800000,0x0,0x3f710908,0xbeac7cd4,0x3f45e403,0xbf226799,0x3f039c3d,0xbf5b941a,0x3ec7c5c2,0xbffb14be,0xbe164083,0xbf7d3aac,0xbef15aea,0xbf61c598,0xbf3daef9,0xbf2beb4a,
0x3f800000,0x0,0x3f6ff573,0xbeb263ef,0x3f41d870,0xbf273656,0x3ef6e0cb,0xbf604621,0x3e964083,0xbffd3aac,0xbe541501,0xbf7a7302,0xbf08f59b,0xbf584853,0xbf4bbbf8,0xbf1b02c6,
0x3f800000,0x0,0x3f6ed89e,0xbeb8442a,0x3f3daef9,0xbf2beb4a,0x3ee63375,0xbf64aa59,0x3e48bd36,0xbffec46d,0xbe888e93,0xbf76ba07,0xbf187fc0,0xbf4d9f02,0xbf584853,0xbf08f59b,
0x3f800000,0x0,0x3f6db293,0xbebe1d4a,0x3f396842,0xbf3085bb,0x3ed53641,0xbf68bf3c,0x3dc8fb30,0xbfffb10f,0xbea68f12,0xbf721352,0xbf273656,0xbf41d870,0xbf633c5a,0xbeebcbbb,
0x3f800000,0x0,0x3f7fffb1,0xbb490fc6,0x3f7ffec4,0xbbc90f88,0x3f7ffd39,0xbc16cb58,0x3ffffb11,0xbcc90e90,0x3f7ff84a,0xbc7b514b,0x3f7ff4e6,0xbc96c9b6,0x3f7ff0e3,0xbcafea69,
0x3f800000,0x0,0x3f7ff84a,0xbc7b514b,0x3f7fe129,0xbcfb49ba,0x3f7fba9e,0xbd3c6dd5,0x3fff84ab,0xbdfb2b74,0x3f7f3f54,0xbd9cecf9,0x3f7eea9d,0xbdbc3ac3,0x3f7e868b,0xbddb7d37,
0x3f800000,0x0,0x3f7fe705,0xbce22a7a,0x3f7f9c18,0xbd621469,0x3f7f1f49,0xbda973ba,0x3ffe70b0,0xbe61bc2e,0x3f7d906e,0xbe0cec4a,0x3f7c7eb0,0xbe28defc,0x3f7b3bab,0xbe44b0b9,
0x3f800000,0x0,0x3f7fcbe2,0xbd2351cb,0x3f7f2f9d,0xbda3308c,0x3f7e2b72,0xbdf475c0,0x3ffcbfc9,0xbea2abb6,0x3f7aed37,0xbe4ada4f,0x3f78b47b,0xbe72b651,0x3f76167a,0xbe8d17c0,
0x3f800000,0x0,0x3f7fa6e3,0xbd55880e,0x3f7e9bc9,0xbdd53db9,0x3f7cdf6c,0xbe1f917b,0x3ffa7302,0xbed41501,0x3f77583a,0xbe840270,0x3f73913f,0xbe9d9e78,0x3f6f20b0,0xbeb6ccc3,
0x3f800000,0x0,0x3f7f7808,0xbd83db0a,0x3f7de0b1,0xbe039502,0x3f7b3bab,0xbe44b0b9,0x3ff78bc5,0xbf027dc0,0x3f72d4eb,0xbea21887,0x3f6d1c1d,0xbec1071e,0x3f666771,0xbedf28a9,
0x3f800000,0x0,0x3f7f3f54,0xbd9cecf9,0x3f7cfe73,0xbe1c76de,0x3f7940c0,0xbe698bba,0x3ff40bdd,0xbf1aa086,0x3f6d67a1,0xbebf926f,0x3f655e0b,0xbee363fa,0x3f5bfb34,0xbf02ef9f,
0x3f800000,0x0,0x3f7efcc9,0xbdb5f8da,0x3f7bf531,0xbe354098,0x3f76ef5b,0xbe870ada,0x3feff573,0xbf3263ef,0x3f671599,0xbedc53c1,0x3f5c61c7,0xbf0242b1,0x3f4fefa8,0xbf1553b7,
0x3f800000,0x0,0x3f7eb069,0xbdcefdb7,0x3f7ac516,0xbe4dee60,0x3f74484b,0xbe9920fe,0x3feb4b0c,0xbf49b953,0x3f5fe4e9,0xbef840c8,0x3f5233c6,0xbf121eb0,0x3f425b89,0xbf269de3,
0x3f800000,0x0,0x3f7e5a38,0xbde7fa9a,0x3f796e4e,0xbe667c66,0x3f714c7a,0xbeab0201,0x3fe60f88,0xbf60924f,0x3f57dc7f,0xbf099f4e,0x3f46e22a,0xbf212ff9,0x3f33587a,0xbf36ad7f,
0x3f800000,0x0,0x3f7dfa38,0xbe007745,0x3f77f110,0xbe7ee6e1,0x3f6dfcf2,0xbebca7af,0x3fe04621,0xbf76e0cb,0x3f4f0417,0xbf16999f,0x3f3a7ca4,0xbf2f61a5,0x3f2302d3,0xbf456439,
0x3f800000,0x0,0x3f7d906e,0xbe0cec4a,0x3f764d97,0xbe8b9507,0x3f6a5ad9,0xbece0bea,0x3fd9f26a,0xbf864b82,0x3f456439,0xbf2302d3,0x3f2d1469,0xbf3ca003,0x3f11796b,0xbf52a649,
0x3f800000,0x0,0x3f7d1cdd,0xbe195be0,0x3f748422,0xbe97a117,0x3f666771,0xbedf28a9,0x3fd31849,0xbf90d3cd,0x3f3b0629,0xbf2ecef7,0x3f1ebc12,0xbf48d8b3,0x3efdbabb,0xbf5e5aa6,
0x3f800000,0x0,0x3f7c9f8a,0xbe25c58c,0x3f7294f8,0xbea395c5,0x3f62241a,0xbeeff7fb,0x3fcbbbf8,0xbf9b02c6,0x3f2ff3e6,0xbf39f2ac,0x3f0f8784,0xbf53fac3,0x3ed6a399,0xbf686b39,
0x3f800000,0x0,0x3f7c187a,0xbe3228d4,0x3f708066,0xbeaf713a,0x3f5d924d,0xbf003a06,0x3fc3e200,0xbfa4d225,0x3f24381a,0xbf446337,0x3eff17b2,0xbf5df6be,0x3eadf73c,0xbf70c501,
0x3f800000,0x0,0x3f7b87b2,0xbe3e853e,0x3f6e46be,0xbebb31a0,0x3f58b3a1,0xbf084b92,0x3fbb8f3b,0xbfae3bde,0x3f17de12,0xbf4e1689,0x3eddbe79,0xbf66becc,0x3e840270,0xbf77583a,
0x3f800000,0x0,0x3f7aed37,0xbe4ada4f,0x3f6be858,0xbec6d529,0x3f5389c7,0xbf102dd5,0x3fb2c8c9,0xbfb73a23,0x3f0af1b7,0xbf570348,0x3ebb31a0,0xbf6e46be,0x3e3228d4,0xbf7c187a,
0x3f800000,0x0,0x3f7a4910,0xbe57278f,0x3f696591,0xbed25a09,0x3f4e1689,0xbf17de12,0x3fa99415,0xbfbfc767,0x3efafef7,0xbf5f20db,0x3e97a117,0xbf748422,0x3db5f8da,0xbf7efcc9,
0x3f800000,0x0,0x3f799b43,0xbe636c83,0x3f66becc,0xbeddbe79,0x3f485bca,0xbf1f599f,0x3f9ff6cb,0xbfc7de65,0x3edf28a9,0xbf666771,0x3e667c66,0xbf796e4e,0x3b490fc6,0xbf7fffb1,
0x3f800000,0x0,0x3f78e3d6,0xbe6fa8b2,0x3f63f473,0xbee900b7,0x3f425b89,0xbf269de3,0x3f95f6d9,0xbfcf7a1f,0x3ec27b55,0xbf6cd007,0x3e1c76de,0xbf7cfe73,0xbda973ba,0xbf7f1f49,
0x3f800000,0x0,0x3f7822d1,0xbe7bdba4,0x3f6106f2,0xbef41f07,0x3f3c17d9,0xbf2da859,0x3f8b9a6b,0xbfd695e5,0x3ea5129f,0xbf725470,0x3da3308c,0xbf7f2f9d,0xbe2bf804,0xbf7c5d3a,
0x3f800000,0x0,0x3f77583a,0xbe840270,0x3f5df6be,0xbeff17b2,0x3f3592e7,0xbf34768f,0x3f80e7e4,0xbfdd2d53,0x3e870ada,0xbf76ef5b,0x3bc90f88,0xbf7ffec4,0xbe80f8c0,0xbf77beb7,
0x3f800000,0x0,0x3f76841b,0xbe8a11f7,0x3f5ac450,0xbf04f484,0x3f2ecef7,0xbf3b0629,0x3f6bcbbb,0xbfe33c5a,0x3e5101f1,0xbf7a9c59,0xbd8a200a,0xbf7f6ac7,0xbeab0201,0xbf714c7a,
0x3f800000,0x0,0x3f75a67b,0xbe901c2c,0x3f577026,0xbf0a48ad,0x3f27ce61,0xbf4154e1,0x3f553641,0xbfe8bf3c,0x3e1324ca,0xbf7d57de,0xbe1008b7,0xbf7d7474,0xbed3c867,0xbf6912ae,
0x3f800000,0x0,0x3f74bf62,0xbe9620d2,0x3f53fac3,0xbf0f8784,0x3f209393,0xbf476085,0x3f3e1d4a,0xbfedb293,0x3da973ba,0xbf7f1f49,0xbe5a3997,0xbf7a1e84,0xbefafef7,0xbf5f20db,
0x3f800000,0x0,0x3f73ced9,0xbe9c1faf,0x3f5064af,0xbf14b039,0x3f19210f,0xbf4d26fd,0x3f268f12,0xbff21352,0x3cafea69,0xbf7ff0e3,0xbe919ddd,0xbf756d97,0xbf102dd5,0xbf5389c7,
0x3f800000,0x0,0x3f72d4eb,0xbea21887,0x3f4cae79,0xbf19c200,0x3f11796b,0xbf52a649,0x3f0e9a22,0xbff5dec6,0xbd2351cb,0xbf7fcbe2,0xbeb554ec,0xbf6f6830,0xbf21cbfb,0xbf466354,
0x3f800000,0x0,0x3f71d19f,0xbea80b1f,0x3f48d8b3,0xbf1ebc12,0x3f099f4e,0xbf57dc7f,0x3eec9a7f,0xbff91298,0xbdcefdb7,0xbf7eb069,0xbed8106b,0xbf6816a8,0xbf3238aa,0xbf37c655,
0x3f800000,0x0,0x3f70c501,0xbeadf73c,0x3f44e3f5,0xbf239da9,0x3f019573,0xbf5cc7d1,0x3ebb6ecf,0xbffbaccd,0xbe25c58c,0xbf7c9f8a,0xbef9a02d,0xbf5f8327,0xbf4154e1,0xbf27ce61,
0x3f800000,0x0,0x3f6faf1b,0xbeb3dca5,0x3f40d0da,0xbf286605,0x3ef2bd43,0xbf61668a,0x3e89cf86,0xbffdabcc,0xbe636c83,0xbf799b43,0xbf0cead0,0xbf55b993,0xbf4f0417,0xbf16999f,
0x3f800000,0x0,0x3f6e8ff8,0xbeb9bb1e,0x3f3ca003,0xbf2d1469,0x3ee1fb6a,0xbf65b710,0x3e2fb680,0xbfff0e58,0xbe901c2c,0xbf75a67b,0xbf1c420c,0xbf4ac77f,0xbf5b2c79,0xbf044889,
0x3f800000,0x0,0x3f6d67a1,0xbebf926f,0x3f385216,0xbf31a81d,0x3ed0eb2a,0xbf69b7e4,0x3d96c32c,0xbfffd397,0xbeadf73c,0xbf70c501,0xbf2ac082,0xbf3ebc1b,0xbf65b710,0xbee1fb6a,
0x3f800000,0x0,0x3f7ffec4,0xbbc90f88,0x3f7ffb11,0xbc490e90,0x3f7ff4e6,0xbc96c9b6,0x3fffec43,0xbd490ab0,0x3f7fe129,0xbcfb49ba,0x3f7fd397,0xbd16c32c,0x3f7fc38f,0xbd2fe007,
0x3f800000,0x0,0x3f7ff4e6,0xbc96c9b6,0x3f7fd397,0xbd16c32c,0x3f7f9c18,0xbd621469,0x3fff4e6d,0xbe16a905,0x3f7eea9d,0xbdbc3ac3,0x3f7e70b0,0xbde1bc2e,0x3f7de0b1,0xbe039502,
0x3f800000,0x0,0x3f7fe129,0xbcfb49ba,0x3f7f84ab,0xbd7b2b74,0x3f7eea9d,0xbdbc3ac3,0x3ffe1324,0xbe7ab273,0x3f7cfe73,0xbe1c76de,0x3f7baccd,0xbe3b6ecf,0x3f7a1e84,0xbe5a3997,
0x3f800000,0x0,0x3f7fc38f,0xbd2fe007,0x3f7f0e58,0xbdafb680,0x3f7de0b1,0xbe039502,0x3ffc3b28,0xbeaf10a2,0x3f7a1e84,0xbe5a3997,0x3f778bc5,0xbe827dc0,0x3f748422,0xbe97a117,
0x3f800000,0x0,0x3f7f9c18,0xbd621469,0x3f7e70b0,0xbde1bc2e,0x3f7c7eb0,0xbe28defc,0x3ff9c79d,0xbee05c13,0x3f764d97,0xbe8b9507,0x3f721352,0xbea68f12,0x3f6d1c1d,0xbec1071e,
0x3f800000,0x0,0x3f7f6ac7,0xbd8a200a,0x3f7dabcc,0xbe09cf86,0x3f7ac516,0xbe4dee60,0x3ff6ba07,0xbf088e93,0x3f718f57,0xbea986c4,0x3f6b4b0c,0xbec9b953,0x3f63f473,0xbee900b7,
0x3f800000,0x0,0x3f7f2f9d,0xbda3308c,0x3f7cbfc9,0xbe22abb6,0x3f78b47b,0xbe72b651,0x3ff31447,0xbf209ae5,0x3f6be858,0xbec6d529,0x3f633c5a,0xbeebcbbb,0x3f591e6a,0xbf07a136,
0x3f800000,0x0,0x3f7eea9d,0xbdbc3ac3,0x3f7baccd,0xbe3b6ecf,0x3f764d97,0xbe8b9507,0x3feed89e,0xbf38442a,0x3f655e0b,0xbee363fa,0x3f59f26a,0xbf064b82,0x3f4cae79,0xbf19c200,
0x3f800000,0x0,0x3f7e9bc9,0xbdd53db9,0x3f7a7302,0xbe541501,0x3f73913f,0xbe9d9e78,0x3fea09a7,0xbf4f7bca,0x3f5df6be,0xbeff17b2,0x3f4f7a1f,0xbf15f6d9,0x3f3ebc1b,0xbf2ac082,
0x3f800000,0x0,0x3f7e4323,0xbdee3876,0x3f791298,0xbe6c9a7f,0x3f708066,0xbeaf713a,0x3fe4aa59,0xbf663375,0x3f55b993,0xbf0cead0,0x3f43e200,0xbf24d225,0x3f2f61a5,0xbf3a7ca4,
0x3f800000,0x0,0x3f7de0b1,0xbe039502,0x3f778bc5,0xbe827dc0,0x3f6d1c1d,0xbec1071e,0x3fdebe05,0xbf7c5d27,0x3f4cae79,0xbf19c200,0x3f373a23,0xbf32c8c9,0x3f1ebc12,0xbf48d8b3,
0x3f800000,0x0,0x3f7d7474,0xbe1008b7,0x3f75dec6,0xbe8e9a22,0x3f696591,0xbed25a09,0x3fd84853,0xbf88f59b,0x3f42de29,0xbf26050a,0x3f299415,0xbf3fc767,0x3f0cead0,0xbf55b993,
0x3f800000,0x0,0x3f7cfe73,0xbe1c76de,0x3f740bdd,0xbe9aa086,0x3f655e0b,0xbee363fa,0x3fd14d3d,0xbf93682a,0x3f385216,0xbf31a81d,0x3f1b02c6,0xbf4bbbf8,0x3ef41f07,0xbf6106f2,
0x3f800000,0x0,0x3f7c7eb0,0xbe28defc,0x3f721352,0xbea68f12,0x3f6106f2,0xbef41f07,0x3fc9d112,0xbf9d7fd1,0x3f2d1469,0xbf3ca003,0x3f0b9a6b,0xbf5695e5,0x3ecc9b8b,0xbf6aab7b,
0x3f800000,0x0,0x3f7bf531,0xbe354098,0x3f6ff573,0xbeb263ef,0x3f5c61c7,0xbf0242b1,0x3fc1d870,0xbfa73656,0x3f212ff9,0xbf46e22a,0x3ef6e0cb,0xbf604621,0x3ea395c5,0xbf7294f8,
0x3f800000,0x0,0x3f7b61fc,0xbe419b37,0x3f6db293,0xbebe1d4a,0x3f577026,0xbf0a48ad,0x3fb96842,0xbfb085bb,0x3f14b039,0xbf5064af,0x3ed53641,0xbf68bf3c,0x3e72b651,0xbf78b47b,
0x3f800000,0x0,0x3f7ac516,0xbe4dee60,0x3f6b4b0c,0xbec9b953,0x3f5233c6,0xbf121eb0,0x3fb085bb,0xbfb96842,0x3f07a136,0xbf591e6a,0x3eb263ef,0xbf6ff573,0x3e1c76de,0xbf7cfe73,
0x3f800000,0x0,0x3f7a1e84,0xbe5a3997,0x3f68bf3c,0xbed53641,0x3f4cae79,0xbf19c200,0x3fa73656,0xbfc1d870,0x3ef41f07,0xbf6106f2,0x3e8e9a22,0xbf75dec6,0x3d8a200a,0xbf7f6ac7,
0x3f800000,0x0,0x3f796e4e,0xbe667c66,0x3f660f88,0xbee0924f,0x3f46e22a,0xbf212ff9,0x3f9d7fd1,0xbfc9d112,0x3ed8106b,0xbf6816a8,0x3e541501,0xbf7a7302,0xbc96c9b6,0xbf7ff4e6,
0x3f800000,0x0,0x3f78b47b,0xbe72b651,0x3f633c5a,0xbeebcbbb,0x3f40d0da,0xbf286605,0x3f93682a,0xbfd14d3d,0x3ebb31a0,0xbf6e46be,0x3e09cf86,0xbf7dabcc,0xbdd53db9,0xbf7e9bc9,
0x3f800000,0x0,0x3f77f110,0xbe7ee6e1,0x3f604621,0xbef6e0cb,0x3f3a7ca4,0xbf2f61a5,0x3f88f59b,0xbfd84853,0x3e9d9e78,0xbf73913f,0x3d7b2b74,0xbf7f84ab,0xbe419b37,0xbf7b61fc,
0x3f800000,0x0,0x3f772417,0xbe8586ce,0x3f5d2d53,0xbf00e7e4,0x3f33e7bc,0xbf36206c,0x3f7c5d27,0xbfdebe05,0x3e7ee6e1,0xbf77f110,0xbc490e90,0xbf7ffb11,0xbe8b9507,0xbf764d97,
0x3f800000,0x0,0x3f764d97,0xbe8b9507,0x3f59f26a,0xbf064b82,0x3f2d1469,0xbf3ca003,0x3f663375,0xbfe4aa59,0x3e419b37,0xbf7b61fc,0xbdafb680,0xbf7f0e58,0xbeb554ec,0xbf6f6830,
0x3f800000,0x0,0x3f756d97,0xbe919ddd,0x3f5695e5,0xbf0b9a6b,0x3f26050a,0xbf42de29,0x3f4f7bca,0xbfea09a7,0x3e039502,0xbf7de0b1,0xbe22abb6,0xbf7cbfc9,0xbeddbe79,0xbf66becc,
0x3f800000,0x0,0x3f748422,0xbe97a117,0x3f531849,0xbf10d3cd,0x3f1ebc12,0xbf48d8b3,0x3f38442a,0xbfeed89e,0x3d8a200a,0xbf7f6ac7,0xbe6c9a7f,0xbf791298,0xbf0242b1,0xbf5c61c7,
0x3f800000,0x0,0x3f73913f,0xbe9d9e78,0x3f4f7a1f,0xbf15f6d9,0x3f173c07,0xbf4e8d90,0x3f209ae5,0xbff31447,0x3bc90f88,0xbf7ffec4,0xbe9aa086,0xbf740bdd,0xbf14b039,0xbf5064af,
0x3f800000,0x0,0x3f7294f8,0xbea395c5,0x3f4bbbf8,0xbf1b02c6,0x3f0f8784,0xbf53fac3,0x3f088e93,0xbff6ba07,0xbd621469,0xbf7f9c18,0xbebe1d4a,0xbf6db293,0xbf26050a,0xbf42de29,
0x3f800000,0x0,0x3f718f57,0xbea986c4,0x3f47de65,0xbf1ff6cb,0x3f07a136,0xbf591e6a,0x3ee05c13,0xbff9c79d,0xbdee3876,0xbf7e4323,0xbee0924f,0xbf660f88,0xbf36206c,0xbf33e7bc,
0x3f800000,0x0,0x3f708066,0xbeaf713a,0x3f43e200,0xbf24d225,0x3eff17b2,0xbf5df6be,0x3eaf10a2,0xbffc3b28,0xbe354098,0xbf7bf531,0xbf00e7e4,0xbf5d2d53,0xbf44e3f5,0xbf239da9,
0x3f800000,0x0,0x3f6f6830,0xbeb554ec,0x3f3fc767,0xbf299415,0x3eee9479,0xbf628210,0x3e7ab273,0xbffe1324,0xbe72b651,0xbf78b47b,0xbf10d3cd,0xbf531849,0xbf5233c6,0xbf121eb0,
0x3f800000,0x0,0x3f6e46be,0xbebb31a0,0x3f3b8f3b,0xbf2e3bde,0x3eddbe79,0xbf66becc,0x3e16a905,0xbfff4e6d,0xbe97a117,0xbf748422,0xbf1ff6cb,0xbf47de65,0xbf5df6be,0xbeff17b2,
0x3f800000,0x0,0x3f6d1c1d,0xbec1071e,0x3f373a23,0xbf32c8c9,0x3ecc9b8b,0xbf6aab7b,0x3d490ab0,0xbfffec43,0xbeb554ec,0xbf6f6830,0xbf2e3bde,0xbf3b8f3b,0xbf6816a8,0xbed8106b,
0x3f800000,0x0,0x3f7ffd39,0xbc16cb58,0x3f7ff4e6,0xbc96c9b6,0x3f7fe705,0xbce22a7a,0x3fffd397,0xbd96c32c,0x3f7fba9e,0xbd3c6dd5,0x3f7f9c18,0xbd621469,0x3f7f7808,0xbd83db0a,
0x3f800000,0x0,0x3f7ff0e3,0xbcafea69,0x3f7fc38f,0xbd2fe007,0x3f7f7808,0xbd83db0a,0x3fff0e58,0xbe2fb680,0x3f7e868b,0xbddb7d37,0x3f7de0b1,0xbe039502,0x3f7d1cdd,0xbe195be0,
0x3f800000,0x0,0x3f7fdaaf,0xbd0a342f,0x3f7f6ac7,0xbd8a200a,0x3f7eb069,0xbdcefdb7,0x3ffdabcc,0xbe89cf86,0x3f7c5d3a,0xbe2bf804,0x3f7ac516,0xbe4dee60,0x3f78e3d6,0xbe6fa8b2,
0x3f800000,0x0,0x3f7fba9e,0xbd3c6dd5,0x3f7eea9d,0xbdbc3ac3,0x3f7d906e,0xbe0cec4a,0x3ffbaccd,0xbebb6ecf,0x3f7940c0,0xbe698bba,0x3f764d97,0xbe8b9507,0x3f72d4eb,0xbea21887,
0x3f800000,0x0,0x3f7f90b1,0xbd6ea038,0x3f7e4323,0xbdee3876,0x3f7c187a,0xbe3228d4,0x3ff91298,0xbeec9a7f,0x3f75341d,0xbe931f35,0x3f708066,0xbeaf713a,0x3f6afb8c,0xbecb2aae,
0x3f800000,0x0,0x3f7f5ce9,0xbd9064b4,0x3f7d7474,0xbe1008b7,0x3f7a4910,0xbe57278f,0x3ff5dec6,0xbf0e9a22,0x3f703b37,0xbeb0eacb,0x3f696591,0xbed25a09,0x3f61668a,0xbef2bd43,
0x3f800000,0x0,0x3f7f1f49,0xbda973ba,0x3f7c7eb0,0xbe28defc,0x3f7822d1,0xbe7bdba4,0x3ff21352,0xbf268f12,0x3f6a5ad9,0xbece0bea,0x3f6106f2,0xbef41f07,0x3f5627fe,0xbf0c42c9,
0x3f800000,0x0,0x3f7ed7d4,0xbdc27c39,0x3f7b61fc,0xbe419b37,0x3f75a67b,0xbe901c2c,0x3fedb293,0xbf3e1d4a,0x3f6398ac,0xbeea6681,0x3f577026,0xbf0a48ad,0x3f495521,0xbf1e1e22,
0x3f800000,0x0,0x3f7e868b,0xbddb7d37,0x3f7a1e84,0xbe5a3997,0x3f72d4eb,0xbea21887,0x3fe8bf3c,0xbf553641,0x3f5bfb34,0xbf02ef9f,0x3f4cae79,0xbf19c200,0x3f3b0629,0xbf2ecef7,
0x3f800000,0x0,0x3f7e2b72,0xbdf475c0,0x3f78b47b,0xbe72b651,0x3f6faf1b,0xbeb3dca5,0x3fe33c5a,0xbf6bcbbb,0x3f5389c7,0xbf102dd5,0x3f40d0da,0xbf286605,0x3f2b561b,0xbf3e35c5,
0x3f800000,0x0,0x3f7dc68c,0xbe06b26e,0x3f772417,0xbe8586ce,0x3f6c3624,0xbec5625c,0x3fdd2d53,0xbf80e7e4,0x3f4a4c87,0xbf1ce11f,0x3f33e7bc,0xbf36206c,0x3f1a6293,0xbf4c3578,
0x3f800000,0x0,0x3f7d57de,0xbe1324ca,0x3f756d97,0xbe919ddd,0x3f686b39,0xbed6a399,0x3fd695e5,0xbf8b9a6b,0x3f404c5c,0xbf28fd41,0x3f26050a,0xbf42de29,0x3f084b92,0xbf58b3a1,
0x3f800000,0x0,0x3f7cdf6c,0xbe1f917b,0x3f73913f,0xbe9d9e78,0x3f644fac,0xbee79a5d,0x3fcf7a1f,0xbf95f6d9,0x3f3592e7,0xbf34768f,0x3f173c07,0xbf4e8d90,0x3eea6681,0xbf6398ac,
0x3f800000,0x0,0x3f7c5d3a,0xbe2bf804,0x3f718f57,0xbea986c4,0x3f5fe4e9,0xbef840c8,0x3fc7de65,0xbf9ff6cb,0x3f2a2a80,0xbf3f41fc,0x3f07a136,0xbf591e6a,0x3ec27b55,0xbf6cd007,
0x3f800000,0x0,0x3f7bd14d,0xbe3857ec,0x3f6f6830,0xbeb554ec,0x3f5b2c79,0xbf044889,0x3fbfc767,0xbfa99415,0x3f1e1e22,0xbf495521,0x3eee9479,0xbf628210,0x3e9920fe,0xbf74484b,
0x3f800000,0x0,0x3f7b3bab,0xbe44b0b9,0x3f6d1c1d,0xbec1071e,0x3f5627fe,0xbf0c42c9,0x3fb73a23,0xbfb2c8c9,0x3f11796b,0xbf52a649,0x3ecc9b8b,0xbf6aab7b,0x3e5d4b1a,0xbf79f35e,
0x3f800000,0x0,0x3f7a9c59,0xbe5101f1,0x3f6aab7b,0xbecc9b8b,0x3f50d937,0xbf140c5f,0x3fae3bde,0xbfbb8f3b,0x3f044889,0xbf5b2c79,0x3ea986c4,0xbf718f57,0x3e06b26e,0xbf7dc68c,
0x3f800000,0x0,0x3f79f35e,0xbe5d4b1a,0x3f6816a8,0xbed8106b,0x3f4b41fa,0xbf1ba299,0x3fa4d225,0xbfc3e200,0x3eed3063,0xbf62df7b,0x3e8586ce,0xbf772417,0x3d3c6dd5,0xbf7fba9e,
0x3f800000,0x0,0x3f7940c0,0xbe698bba,0x3f655e0b,0xbee363fa,0x3f456439,0xbf2302d3,0x3f9b02c6,0xbfcbbbf8,0x3ed0eb2a,0xbf69b7e4,0x3e419b37,0xbf7b61fc,0xbd2351cb,0xbf7fcbe2,
0x3f800000,0x0,0x3f788486,0xbe75c35a,0x3f628210,0xbeee9479,0x3f3f41fc,0xbf2a2a80,0x3f90d3cd,0xbfd31849,0x3eb3dca5,0xbf6faf1b,0x3dee3876,0xbf7e4323,0xbe007745,0xbf7dfa38,
0x3f800000,0x0,0x3f77beb7,0xbe80f8c0,0x3f5f8327,0xbef9a02d,0x3f38dd65,0xbf311722,0x3f864b82,0xbfd9f26a,0x3e9620d2,0xbf74bf62,0x3d2fe007,0xbf7fc38f,0xbe57278f,0xbf7a4910,
0x3f800000,0x0,0x3f76ef5b,0xbe870ada,0x3f5c61c7,0xbf0242b1,0x3f3238aa,0xbf37c655,0x3f76e0cb,0xbfe04621,0x3e6fa8b2,0xbf78e3d6,0xbcfb49ba,0xbf7fe129,0xbe9620d2,0xbf74bf62,
0x3f800000,0x0,0x3f76167a,0xbe8d17c0,0x3f591e6a,0xbf07a136,0x3f2b561b,0xbf3e35c5,0x3f60924f,0xbfe60f88,0x3e3228d4,0xbf7c187a,0xbdd53db9,0xbf7e9bc9,0xbebf926f,0xbf6d67a1,
0x3f800000,0x0,0x3f75341d,0xbe931f35,0x3f55b993,0xbf0cead0,0x3f24381a,0xbf446337,0x3f49b953,0xbfeb4b0c,0x3de7fa9a,0xbf7e5a38,0xbe354098,0xbf7bf531,0xbee79a5d,0xbf644fac,
0x3f800000,0x0,0x3f74484b,0xbe9920fe,0x3f5233c6,0xbf121eb0,0x3f1ce11f,0xbf4a4c87,0x3f3263ef,0xbfeff573,0x3d55880e,0xbf7fa6e3,0xbe7ee6e1,0xbf77f110,0xbf06f686,0xbf5988ad,
0x3f800000,0x0,0x3f73530e,0xbe9f1cdf,0x3f4e8d90,0xbf173c07,0x3f1553b7,0xbf4fefa8,0x3f1aa086,0xbff40bdd,0xbc16cb58,0xbf7ffd39,0xbea395c5,0xbf7294f8,0xbf19210f,0xbf4d26fd,
0x3f800000,0x0,0x3f725470,0xbea5129f,0x3f4ac77f,0xbf1c420c,0x3f0d9281,0xbf554aa4,0x3f027dc0,0xbff78bc5,0xbd9064b4,0xbf7f5ce9,0xbec6d529,0xbf6be858,0xbf2a2a80,0xbf3f41fc,
0x3f800000,0x0,0x3f714c7a,0xbeab0201,0x3f46e22a,0xbf212ff9,0x3f05a02c,0xbf5a5ba0,0x3ed41501,0xbffa7302,0xbe06b26e,0xbf7dc68c,0xbee900b7,0xbf63f473,0xbf39f2ac,0xbf2ff3e6,
0x3f800000,0x0,0x3f703b37,0xbeb0eacb,0x3f42de29,0xbf26050a,0x3efafef7,0xbf5f20db,0x3ea2abb6,0xbffcbfc9,0xbe44b0b9,0xbf7b3bab,0xbf04f484,0xbf5ac450,0xbf485bca,0xbf1f599f,
0x3f800000,0x0,0x3f6f20b0,0xbeb6ccc3,0x3f3ebc1b,0xbf2ac082,0x3eea6681,0xbf6398ac,0x3e61bc2e,0xbffe70b0,0xbe80f8c0,0xbf77beb7,0xbf14b039,0xbf5064af,0xbf554aa4,0xbf0d9281,
0x3f800000,0x0,0x3f6dfcf2,0xbebca7af,0x3f3a7ca4,0xbf2f61a5,0x3ed97cb9,0xbf67c187,0x3dfb2b74,0xbfff84ab,0xbe9f1cdf,0xbf73530e,0xbf239da9,0xbf44e3f5,0xbf60a6cf,0xbef58035,
0x3f800000,0x0,0x3f6cd007,0xbec27b55,0x3f36206c,0xbf33e7bc,0x3ec8477c,0xbf6b99fb,0x3cc90e90,0xbffffb11,0xbebca7af,0xbf6dfcf2,0xbf31a81d,0xbf385216,0xbf6a5ad9,0xbece0bea,
0x3f800000,0x0,0x0,0x0,0x0,0x0,0x0,0x0,0x0,0x0,0x0,0x0,0x0,0x0,0x0,0x0,
0x0,0x0,0x0,0x0,0x0,0x0,0x0,0x0,0x0,0x0,0x0,0x0,0x0,0x0,0x0,0x0,
0x0,0x0,0x3e000000,0xbf20dff7,0x3ed0c429,0x0,0x3e000000,0x3e61f78b,0x3e0a8bd4,0x0,0x3e000000,0x3d5413cd,0x3d5df9ad,0x0,0x3e000000,0x3cf043ab,
0x0,0x0,0x3e000000,0x3ccbafaf,0xbd5df9ad,0x0,0x3e000000,0x3cf043ab,0xbe0a8bd4,0x0,0x3e000000,0x3d5413cd,0xbed0c429,0x0,0x3e000000,0x3e61f78b,
0x0,0x0,0x0,0x0,0x3f000000,0x0,0x0,0x3f000000,0x0,0x0,0x0,0x0,0x0,0x0,0x0,0x0,
0x0,0x0,0x0,0x0,0x0,0x0,0x0,0x0,0x0,0x0,0x0,0x0,0x3f000000,0x0,0x0,0xbf000000,
0x0,0x0,0x3e000000,0xbe3f90c7,0xbe8b7e3f,0x0,0x3e000000,0xbeb641af,0x3ea73d75,0x0,0x3e000000,0x3e9a827a,0x3da61ad1,0x0,0x3e000000,0x3dd906bd,
0x0,0x0,0x3e000000,0x3dab0dc1,0xbda61ad1,0x0,0x3e000000,0x3dd906bd,0xbea73d75,0x0,0x3e000000,0x3e9a827a,0x3e8b7e3f,0x0,0x3e000000,0xbeb641af,
0x0,0x0,0x0,0x0,0x0,0x0,0x0,0x0,0x3f000000,0x0,0x0,0x3f000000,0x0,0x0,0x0,0x0,
0x0,0x0,0x0,0x0,0x0,0x0,0x0,0x0,0x3f000000,0x0,0x0,0xbf000000,0x0,0x0,0x0,0x0,
0x0,0x0,0x3e000000,0xbdab0dc1,0xbda61ad1,0x0,0x3e000000,0xbdd906bd,0xbea73d75,0x0,0x3e000000,0xbe9a827a,0x3e8b7e3f,0x0,0x3e000000,0x3eb641af,
0x0,0x0,0x3e000000,0x3e3f90c7,0xbe8b7e3f,0x0,0x3e000000,0x3eb641af,0x3ea73d75,0x0,0x3e000000,0xbe9a827a,0x3da61ad1,0x0,0x3e000000,0xbdd906bd,
0x0,0x0,0x0,0x0,0x0,0x0,0x0,0x0,0x0,0x0,0x0,0x0,0x3f000000,0x0,0x0,0x3f000000,
0x0,0x0,0x0,0x0,0x3f000000,0x0,0x0,0xbf000000,0x0,0x0,0x0,0x0,0x0,0x0,0x0,0x0,
0x0,0x0,0x3e000000,0xbccbafaf,0xbd5df9ad,0x0,0x3e000000,0xbcf043ab,0xbe0a8bd4,0x0,0x3e000000,0xbd5413cd,0xbed0c429,0x0,0x3e000000,0xbe61f78b,
0x0,0x0,0x3e000000,0x3f20dff7,0x3ed0c429,0x0,0x3e000000,0xbe61f78b,0x3e0a8bd4,0x0,0x3e000000,0xbd5413cd,0x3d5df9ad,0x0,0x3e000000,0xbcf043ab,
};

struct Params {
    const __nv_bfloat16 *wr, *wi, *lre, *lim, *ldt, *dsk;
    float* out;
};

struct cf { float x, y; };
#define YIELD() asm volatile("pmevent 1;")
#define YS 14
#define YIELD_S1() do { if (YS & 1) YIELD(); } while (0)
#define YIELD_S2() do { if (YS & 2) YIELD(); } while (0)
#define YIELD_S3() do { if (YS & 4) YIELD(); } while (0)
__device__ __forceinline__ uint32_t smem_u32(const void* p) { return (uint32_t)__cvta_generic_to_shared(p); }
__device__ __forceinline__ void mbar_init(uint32_t a, uint32_t c) { asm volatile("mbarrier.init.shared::cta.b64 [%0], %1;" ::"r"(a), "r"(c) : "memory"); }
__device__ __forceinline__ void mbar_expect_tx(uint32_t a, uint32_t b) { asm volatile("mbarrier.arrive.expect_tx.shared::cta.b64 _, [%0], %1;" ::"r"(a), "r"(b) : "memory"); }
__device__ __forceinline__ void mbar_arrive(uint32_t a) { asm volatile("mbarrier.arrive.shared::cta.b64 _, [%0];" ::"r"(a) : "memory"); }
__device__ __forceinline__ void warp_arrive(uint32_t a) {
    __syncwarp();
    asm volatile("{.reg .pred p; elect.sync _|p, 0xffffffff; @p mbarrier.arrive.shared::cta.b64 _, [%0];}" ::"r"(a) : "memory");
}
__device__ __forceinline__ uint32_t mbar_try(uint32_t a, uint32_t ph) {
    uint32_t ok;
    asm volatile("{.reg .pred p; mbarrier.try_wait.parity.shared::cta.b64 p, [%1], %2; selp.u32 %0, 1, 0, p;}" : "=r"(ok) : "r"(a), "r"(ph) : "memory");
    return ok;
}
__device__ __forceinline__ void mbar_wait(uint32_t a, uint32_t ph) {
    uint32_t ok, n = 0;
    do { ok = mbar_try(a, ph); } while (!ok && ++n < SPIN_LIMIT);
}
__device__ __forceinline__ void mbar_wait_fast(uint32_t a, uint32_t ph) { if (!mbar_try(a, ph)) mbar_wait(a, ph); }
__device__ __forceinline__ unsigned ld_rlx(const unsigned* p) { unsigned v; asm volatile("ld.relaxed.gpu.global.u32 %0, [%1];" : "=r"(v) : "l"(p) : "memory"); return v; }
__device__ __forceinline__ void wait_cnt(const unsigned* p, unsigned target) {
    unsigned n = 0;
    while ((int)(ld_rlx(p) - target) < 0 && ++n < SPIN_LIMIT) __nanosleep(20);
}
__device__ __forceinline__ void red_hint(unsigned* p) { asm volatile("red.relaxed.gpu.global.add.u32 [%0], 1;" ::"l"(p) : "memory"); }
__device__ __forceinline__ void fence_async_sm() { asm volatile("fence.proxy.async.shared::cta;" ::: "memory"); }
#define bar_sync(id, n) asm volatile("bar.sync %0, %1;" ::"n"(id), "n"(n) : "memory")
#define bar_arrive(id, n) asm volatile("bar.arrive %0, %1;" ::"n"(id), "n"(n) : "memory")
__device__ __forceinline__ bool elect_one() {
    uint32_t r;
    asm volatile("{.reg .pred p; elect.sync _|p, 0xffffffff; selp.u32 %0, 1, 0, p;}" : "=r"(r));
    return r != 0;
}

__device__ __forceinline__ void tma2d(uint32_t dst, const CUtensorMap* m, int c0, int c1, uint32_t bar) {
    asm volatile("cp.async.bulk.tensor.2d.shared::cluster.global.mbarrier::complete_tx::bytes [%0], [%1, {%3,%4}], [%2];" ::"r"(dst), "l"(m), "r"(bar), "r"(c0), "r"(c1) : "memory");
}
__device__ __forceinline__ void tma3d(uint32_t dst, const CUtensorMap* m, int c0, int c1, int c2, uint32_t bar) {
    asm volatile("cp.async.bulk.tensor.3d.shared::cluster.global.mbarrier::complete_tx::bytes [%0], [%1, {%3,%4,%5}], [%2];" ::"r"(dst), "l"(m), "r"(bar), "r"(c0), "r"(c1), "r"(c2) : "memory");
}
__device__ __forceinline__ void tma4d_mc(uint32_t dst, const CUtensorMap* m, int c0, int c1, int c2, int c3, uint32_t bar) {
    asm volatile("cp.async.bulk.tensor.4d.shared::cluster.global.mbarrier::complete_tx::bytes.multicast::cluster [%0], [%1, {%3,%4,%5,%6}], [%2], %7;" ::"r"(dst), "l"(m), "r"(bar), "r"(c0), "r"(c1), "r"(c2), "r"(c3), "h"((uint16_t)3) : "memory");
}
__device__ __forceinline__ void tma4d(uint32_t dst, const CUtensorMap* m, int c0, int c1, int c2, int c3, uint32_t bar) {
    asm volatile("cp.async.bulk.tensor.4d.shared::cluster.global.mbarrier::complete_tx::bytes [%0], [%1, {%3,%4,%5,%6}], [%2];" ::"r"(dst), "l"(m), "r"(bar), "r"(c0), "r"(c1), "r"(c2), "r"(c3) : "memory");
}
__device__ __forceinline__ void tma2d_st(const CUtensorMap* m, int c0, int c1, uint32_t src) {
    asm volatile("cp.async.bulk.tensor.2d.global.shared::cta.bulk_group [%0, {%2,%3}], [%1];" ::"l"(m), "r"(src), "r"(c0), "r"(c1) : "memory");
}
__device__ __forceinline__ void tma5d(uint32_t dst, const CUtensorMap* m, int c0, int c1, int c2, int c3, int c4, uint32_t bar) {
    asm volatile("cp.async.bulk.tensor.5d.shared::cluster.global.mbarrier::complete_tx::bytes [%0], [%1, {%3,%4,%5,%6,%7}], [%2];" ::"r"(dst), "l"(m), "r"(bar), "r"(c0), "r"(c1), "r"(c2), "r"(c3), "r"(c4) : "memory");
}
__device__ __forceinline__ void bulk_ld(uint32_t dst, const void* src, uint32_t n, uint32_t bar) {
    asm volatile("cp.async.bulk.shared::cluster.global.mbarrier::complete_tx::bytes [%0], [%1], %2, [%3];" ::"r"(dst), "l"(src), "r"(n), "r"(bar) : "memory");
}
__device__ __forceinline__ void bulk_st(void* dst, uint32_t src, uint32_t n) {
    asm volatile("cp.async.bulk.global.shared::cta.bulk_group [%0], [%1], %2;" ::"l"(dst), "r"(src), "r"(n) : "memory");
}
__device__ __forceinline__ void bulk_commit() { asm volatile("cp.async.bulk.commit_group;" ::: "memory"); }
__device__ __forceinline__ void bulk_wait_read() { asm volatile("cp.async.bulk.wait_group.read 0;" ::: "memory"); }
__device__ __forceinline__ void bulk_wait_all() { asm volatile("cp.async.bulk.wait_group 0;" ::: "memory"); }
__device__ __forceinline__ void stsm4(uint32_t a, uint32_t r0, uint32_t r1, uint32_t r2, uint32_t r3) {
    asm volatile("stmatrix.sync.aligned.m8n8.x4.shared.b16 [%0], {%1,%2,%3,%4};" ::"r"(a), "r"(r0), "r"(r1), "r"(r2), "r"(r3) : "memory");
}
__device__ __forceinline__ void sts128(uint32_t a, uint32_t r0, uint32_t r1, uint32_t r2, uint32_t r3) {
    asm volatile("st.shared.v4.b32 [%0], {%1,%2,%3,%4};" ::"r"(a), "r"(r0), "r"(r1), "r"(r2), "r"(r3) : "memory");
}
__device__ __forceinline__ void lds128f(uint32_t a, float& x, float& y, float& z, float& u) { asm volatile("ld.shared.v4.f32 {%0,%1,%2,%3}, [%4];" : "=f"(x), "=f"(y), "=f"(z), "=f"(u) : "r"(a) : "memory"); }
__device__ __forceinline__ cf lds_cf(uint32_t a) { cf v; asm volatile("ld.shared.v2.f32 {%0,%1}, [%2];" : "=f"(v.x), "=f"(v.y) : "r"(a) : "memory"); return v; }
__device__ __forceinline__ void stg128(const void* a, uint32_t r0, uint32_t r1, uint32_t r2, uint32_t r3) {
    asm volatile("st.global.v4.b32 [%0], {%1,%2,%3,%4};" ::"l"(a), "r"(r0), "r"(r1), "r"(r2), "r"(r3) : "memory");
}
__device__ __forceinline__ int fresh_lane() { int v; asm volatile("mov.u32 %0, %%laneid;" : "=r"(v)); return v; }
__device__ __forceinline__ uint32_t opaque32(uint32_t v) { asm volatile("" : "+r"(v)); return v; }
__device__ __forceinline__ const uint8_t* padd(const void* base, uint32_t off) {
    uint64_t r;
    asm("{.reg .u32 l, h; mov.b64 {l, h}, %1; add.cc.u32 l, l, %2; addc.u32 h, h, 0; mov.b64 %0, {l, h};}" : "=l"(r) : "l"(base), "r"(off));
    return (const uint8_t*)r;
}
template <int N, int STRIDE> __device__ __forceinline__ void ldtab(uint32_t (&v)[4 * N], uint32_t off) {
    const uint8_t* a = padd(g_tab, off);
#pragma unroll
    for (int i = 0; i < N; i++)
        asm volatile("ld.global.nc.v4.b32 {%0,%1,%2,%3}, [%4];" : "=r"(v[4 * i]), "=r"(v[4 * i + 1]), "=r"(v[4 * i + 2]), "=r"(v[4 * i + 3]) : "l"(a + i * STRIDE));
}
template <int STRIDE> __device__ __forceinline__ void ldtab_cf(cf (&t)[8], uint32_t off) {
    uint32_t v[16];
    ldtab<4, STRIDE>(v, off);
#pragma unroll
    for (int i = 0; i < 8; i++) t[i] = {__uint_as_float(v[2 * i]), __uint_as_float(v[2 * i + 1])};
}
__device__ __forceinline__ uint32_t lds16(uint32_t a) { uint32_t v; asm volatile("ld.shared.u16 %0, [%1];" : "=r"(v) : "r"(a)); return v; }
__device__ __forceinline__ unsigned get_epoch(uint32_t bars) {
    mbar_wait(bars + B_EP, 0);
    unsigned e;
    asm volatile("ld.shared.u32 %0, [%1];" : "=r"(e) : "r"(bars + B_EPOCH) : "memory");
    return e;
}
__device__ __forceinline__ void sts64(uint32_t a, uint32_t x, uint32_t y) { asm volatile("st.shared.v2.b32 [%0], {%1,%2};" ::"r"(a), "r"(x), "r"(y) : "memory"); }
__device__ __forceinline__ uint32_t pk(float lo, float hi) { uint32_t r; asm("cvt.rn.bf16x2.f32 %0, %1, %2;" : "=r"(r) : "f"(hi), "f"(lo)); return r; }
__device__ __forceinline__ float bf2f(unsigned short v) { return __uint_as_float((uint32_t)v << 16); }

__device__ __forceinline__ uint64_t mkdesc(uint32_t addr, uint32_t lbo, uint32_t sbo, uint32_t swz) {
    return (uint64_t)((addr & 0x3FFFF) >> 4) | ((uint64_t)(lbo >> 4) << 16) | ((uint64_t)(sbo >> 4) << 32) | ((uint64_t)swz << 62);
}
__device__ __forceinline__ uint64_t opaque(uint64_t v) { asm volatile("" : "+l"(v)); return v; }
__device__ __forceinline__ void wg_fence() { asm volatile("wgmma.fence.sync.aligned;" ::: "memory"); }
__device__ __forceinline__ void wg_commit() { asm volatile("wgmma.commit_group.sync.aligned;" ::: "memory"); }
template <int N> __device__ __forceinline__ void wg_wait() { asm volatile("wgmma.wait_group.sync.aligned %0;" ::"n"(N) : "memory"); }
template <int N> __device__ __forceinline__ void pin(float (&d)[N]) {
#pragma unroll
    for (int i = 0; i < N; i++) asm volatile("" : "+f"(d[i])::"memory");
}
template <int N> __device__ __forceinline__ void pinu(uint32_t (&d)[N]) {
#pragma unroll
    for (int i = 0; i < N; i++) asm volatile("" : "+r"(d[i])::"memory");
}

#define R8(d, o) "+f"(d[o]), "+f"(d[o + 1]), "+f"(d[o + 2]), "+f"(d[o + 3]), "+f"(d[o + 4]), "+f"(d[o + 5]), "+f"(d[o + 6]), "+f"(d[o + 7])
#define L8 "%0,%1,%2,%3,%4,%5,%6,%7"
#define L32 L8 ",%8,%9,%10,%11,%12,%13,%14,%15,%16,%17,%18,%19,%20,%21,%22,%23,%24,%25,%26,%27,%28,%29,%30,%31"
#define L56 L32 ",%32,%33,%34,%35,%36,%37,%38,%39,%40,%41,%42,%43,%44,%45,%46,%47,%48,%49,%50,%51,%52,%53,%54,%55"
#define L64 L56 ",%56,%57,%58,%59,%60,%61,%62,%63"

template <int O, int TA, int TB, int N> __device__ __forceinline__ void mma128_ss(float (&d)[N], uint64_t da, uint64_t db, int sc) {
    asm volatile("{.reg .pred p; setp.ne.b32 p, %66, 0;\n"
                 "wgmma.mma_async.sync.aligned.m64n128k16.f32.bf16.bf16 {" L64 "}, %64, %65, p, 1, 1, %67, %68;}"
                 : R8(d, O), R8(d, O + 8), R8(d, O + 16), R8(d, O + 24), R8(d, O + 32), R8(d, O + 40), R8(d, O + 48), R8(d, O + 56)
                 : "l"(da), "l"(db), "r"(sc), "n"(TA), "n"(TB));
}
template <int O, int TB> __device__ __forceinline__ void mma128_rs(float (&d)[128], uint32_t a0, uint32_t a1, uint32_t a2, uint32_t a3, uint64_t db, int sc) {
    asm volatile("{.reg .pred p; setp.ne.b32 p, %69, 0;\n"
                 "wgmma.mma_async.sync.aligned.m64n128k16.f32.bf16.bf16 {" L64 "}, {%64,%65,%66,%67}, %68, p, 1, 1, %70;}"
                 : R8(d, O), R8(d, O + 8), R8(d, O + 16), R8(d, O + 24), R8(d, O + 32), R8(d, O + 40), R8(d, O + 48), R8(d, O + 56)
                 : "r"(a0), "r"(a1), "r"(a2), "r"(a3), "l"(db), "r"(sc), "n"(TB));
}
template <int TB> __device__ __forceinline__ void mma64_rs(float (&d)[32], uint32_t a0, uint32_t a1, uint32_t a2, uint32_t a3, uint64_t db, int sc) {
    asm volatile("{.reg .pred p; setp.ne.b32 p, %37, 0;\n"
                 "wgmma.mma_async.sync.aligned.m64n64k16.f32.bf16.bf16 {" L32 "}, {%32,%33,%34,%35}, %36, p, 1, 1, %38;}"
                 : R8(d, 0), R8(d, 8), R8(d, 16), R8(d, 24)
                 : "r"(a0), "r"(a1), "r"(a2), "r"(a3), "l"(db), "r"(sc), "n"(TB));
}
__device__ __forceinline__ void mma112_ss(float (&d)[64], uint64_t da, uint64_t db, int sc) {
    asm volatile("{.reg .pred p; setp.ne.b32 p, %58, 0;\n"
                 "wgmma.mma_async.sync.aligned.m64n112k16.f32.bf16.bf16 {" L56 "}, %56, %57, p, 1, 1, 0, 1;}"
                 : R8(d, 8), R8(d, 16), R8(d, 24), R8(d, 32), R8(d, 40), R8(d, 48), R8(d, 56)
                 : "l"(da), "l"(db), "r"(sc));
}
__device__ __forceinline__ void mma16_rs(float (&d)[64], uint32_t a0, uint32_t a1, uint32_t a2, uint32_t a3, uint64_t db, int sc) {
    asm volatile("{.reg .pred p; setp.ne.b32 p, %13, 0;\n"
                 "wgmma.mma_async.sync.aligned.m64n16k16.f32.bf16.bf16 {" L8 "}, {%8,%9,%10,%11}, %12, p, 1, 1, 1;}"
                 : R8(d, 0)
                 : "r"(a0), "r"(a1), "r"(a2), "r"(a3), "l"(db), "r"(sc));
}

__device__ __forceinline__ cf cmul(cf a, cf b) { return {fmaf(a.x, b.x, -a.y * b.y), fmaf(a.x, b.y, a.y * b.x)}; }
__device__ __forceinline__ cf cmulc(cf a, cf b) { return {fmaf(a.x, b.x, a.y * b.y), fmaf(a.y, b.x, -a.x * b.y)}; }
__device__ __forceinline__ cf cfma(cf a, cf b, cf c) { return {fmaf(a.x, b.x, fmaf(-a.y, b.y, c.x)), fmaf(a.x, b.y, fmaf(a.y, b.x, c.y))}; }
__device__ __forceinline__ cf csq(cf a) { return {fmaf(a.x, a.x, -a.y * a.y), (a.x * a.y) * 2.f}; }
__device__ __forceinline__ cf csel(int c, cf a, cf b) {
    cf r;
    asm("{.reg .pred p; setp.ne.s32 p, %2, 0; selp.f32 %0, %3, %5, p; selp.f32 %1, %4, %6, p;}" : "=f"(r.x), "=f"(r.y) : "r"(c), "f"(a.x), "f"(a.y), "f"(b.x), "f"(b.y));
    return r;
}
__device__ __forceinline__ cf cadd(cf a, cf b) { return {a.x + b.x, a.y + b.y}; }
__device__ __forceinline__ cf csub(cf a, cf b) { return {a.x - b.x, a.y - b.y}; }
__device__ __forceinline__ cf twice_minus(cf a, cf s) { return {fmaf(2.f, a.x, -s.x), fmaf(2.f, a.y, -s.y)}; }
__device__ __forceinline__ cf twid(int m, int M) {
    int r = ((m + M / 2) & (M - 1)) - M / 2;
    float s, c;
    __sincosf((float)r * (-6.283185307179586f / (float)M), &s, &c);
    return {c, s};
}
struct c2 { cf a, b; };
#define YP1 3
#define YP3 3
template <int Y> __device__ __forceinline__ void fin(c2& u) { if (Y & 1) asm volatile("pmevent 1;" : "+f"(u.a.x), "+f"(u.a.y), "+f"(u.b.x), "+f"(u.b.y)); }
template <int Y> __device__ __forceinline__ void fin(c2& u, c2& v) {
    if (Y & 2) asm volatile("pmevent 1;" : "+f"(u.a.x), "+f"(u.a.y), "+f"(u.b.x), "+f"(u.b.y), "+f"(v.a.x), "+f"(v.a.y), "+f"(v.b.x), "+f"(v.b.y));
}
__device__ __forceinline__ c2 mul2(c2 u, cf t) { return {cmul(u.a, t), cmul(u.b, t)}; }
__device__ __forceinline__ c2 mul2(c2 u, c2 t) { return {cmul(u.a, t.a), cmul(u.b, t.b)}; }
__device__ __forceinline__ c2 fma2(c2 u, cf t, c2 c) { return {cfma(u.a, t, c.a), cfma(u.b, t, c.b)}; }
__device__ __forceinline__ c2 fma2(c2 u, c2 t, c2 c) { return {cfma(u.a, t.a, c.a), cfma(u.b, t.b, c.b)}; }
__device__ __forceinline__ c2 twm2(c2 u, c2 s) { return {twice_minus(u.a, s.a), twice_minus(u.b, s.b)}; }
template <int Y> __device__ __forceinline__ void bfly(c2& u, c2& v) { const c2 t = u; u = {cadd(t.a, v.a), cadd(t.b, v.b)}; v = {csub(t.a, v.a), csub(t.b, v.b)}; fin<Y>(u, v); }
template <int Y> __device__ __forceinline__ void bfly_mi(c2& u, c2& v) {
    const c2 t = u, z = v;
    u = {{t.a.x + z.a.y, t.a.y - z.a.x}, {t.b.x + z.b.y, t.b.y - z.b.x}};
    v = {{t.a.x - z.a.y, t.a.y + z.a.x}, {t.b.x - z.b.y, t.b.y + z.b.x}};
    fin<Y>(u, v);
}
template <int Y> __device__ __forceinline__ void bfly_s(c2& u, c2& v) {
    const float s = 0.70710678118654752f;
    const c2 t = u, z = v;
    u = {{fmaf(s, z.a.x, t.a.x), fmaf(s, z.a.y, t.a.y)}, {fmaf(s, z.b.x, t.b.x), fmaf(s, z.b.y, t.b.y)}};
    v = {{fmaf(-s, z.a.x, t.a.x), fmaf(-s, z.a.y, t.a.y)}, {fmaf(-s, z.b.x, t.b.x), fmaf(-s, z.b.y, t.b.y)}};
    fin<Y>(u, v);
}
template <int Y, class T> __device__ __forceinline__ void bfly_tw(c2& u0, c2& v0, T t0, c2& u1, c2& v1, T t1) {
    v0 = fma2(v0, t0, u0); fin<Y>(v0);
    v1 = fma2(v1, t1, u1); fin<Y>(v1);
    const c2 a = twm2(u0, v0), b = twm2(u1, v1);
    u0 = v0; u1 = v1; v0 = a; v1 = b;
    fin<Y>(v0, v1);
}
template <bool TW, int Y> __device__ __forceinline__ void dft8(c2 (&v)[8], const cf (&tw)[8]) {
    if (TW) {
#pragma unroll
        for (int n = 1; n < 4; n++) { v[n] = mul2(v[n], tw[n]); fin<Y>(v[n]); }
        bfly_tw<Y>(v[0], v[4], tw[4], v[2], v[6], tw[6]);
        bfly_tw<Y>(v[1], v[5], tw[5], v[3], v[7], tw[7]);
    } else {
#pragma unroll
        for (int n = 0; n < 4; n++) bfly<Y>(v[n], v[n + 4]);
    }
    bfly<Y>(v[0], v[2]); bfly_mi<Y>(v[4], v[6]);
    bfly<Y>(v[1], v[3]); bfly_mi<Y>(v[5], v[7]);
    v[5] = {{v[5].a.x + v[5].a.y, v[5].a.y - v[5].a.x}, {v[5].b.x + v[5].b.y, v[5].b.y - v[5].b.x}};
    v[7] = {{v[7].a.y - v[7].a.x, -v[7].a.x - v[7].a.y}, {v[7].b.y - v[7].b.x, -v[7].b.x - v[7].b.y}};
    fin<Y>(v[5], v[7]);
    bfly<Y>(v[0], v[1]); bfly_s<Y>(v[4], v[5]); bfly_mi<Y>(v[2], v[3]); bfly_s<Y>(v[6], v[7]);
    const c2 t1 = v[1], t3 = v[3];
    v[1] = v[4]; v[4] = t1; v[3] = v[6]; v[6] = t3;
}

__device__ __forceinline__ void gather(uint64_t (&fv)[4], const uint8_t* a, int n) {
    asm volatile("{.reg .pred p0, p1, p2, p3;\n"
                 "setp.ge.s32 p0, %5, 0; setp.ge.s32 p1, %5, 4; setp.ge.s32 p2, %5, 8; setp.ge.s32 p3, %5, 12;\n"
                 "@p0 ld.relaxed.gpu.global.b64 %0, [%4]; @p1 ld.relaxed.gpu.global.b64 %1, [%4+-32768];\n"
                 "@p2 ld.relaxed.gpu.global.b64 %2, [%4+-65536]; @p3 ld.relaxed.gpu.global.b64 %3, [%4+-98304];}"
                 : "+l"(fv[0]), "+l"(fv[1]), "+l"(fv[2]), "+l"(fv[3]) : "l"(a), "r"(n) : "memory");
}
__device__ __forceinline__ cf as_cf(uint64_t v) { cf r; asm("mov.b64 {%0,%1}, %2;" : "=f"(r.x), "=f"(r.y) : "l"(v)); return r; }
template <int H> __device__ __forceinline__ void prescale(float (&u)[64], const float (&d)[128], cf gam) {
#pragma unroll
    for (int i = 0; i < 32; i += 2) {
        const int r = 2 * i + 2 * H;
        c2 v = mul2(c2{{d[r], -d[64 + r]}, {d[r + 1], -d[65 + r]}}, gam);
        if (YS & 2) asm volatile("pmevent 1;" : "+f"(v.a.x), "+f"(v.a.y), "+f"(v.b.x), "+f"(v.b.y));
        u[i] = v.a.x; u[32 + i] = v.a.y; u[i + 1] = v.b.x; u[33 + i] = v.b.y;
    }
}
__device__ __forceinline__ void scan2(const float (&u)[64], cf lam, cf st, const uint8_t* hptr, uint32_t hm, uint32_t hb, uint32_t& keep) {
    uint32_t hp[32];
#pragma unroll
    for (int jj = 0; jj < 4; jj++) {
        cf v[8];
#pragma unroll
        for (int i = 0; i < 8; i++) v[i] = st = cfma(lam, st, {u[8 * jj + i], u[32 + 8 * jj + i]});
        const int o = 8 * jj;
        hp[o] = pk(v[0].x, v[2].x); hp[o + 1] = pk(v[4].x, v[6].x); hp[o + 2] = pk(v[1].x, v[3].x); hp[o + 3] = pk(v[5].x, v[7].x);
        hp[o + 4] = pk(v[0].y, v[2].y); hp[o + 5] = pk(v[4].y, v[6].y); hp[o + 6] = pk(v[1].y, v[3].y); hp[o + 7] = pk(v[5].y, v[7].y);
        hp[o + jj] = (hp[o + jj] & hm) | hb;
        hp[o + 4 + jj] = (hp[o + 4 + jj] & hm) | hb;
        stg128(hptr + (jj >> 1) * 8192 + (jj & 1) * 512, hp[o], hp[o + 1], hp[o + 2], hp[o + 3]);
        stg128(hptr + 16384 + (jj >> 1) * 8192 + (jj & 1) * 512, hp[o + 4], hp[o + 5], hp[o + 6], hp[o + 7]);
        YIELD_S3();
        if (jj > 0) {
#pragma unroll
            for (int i = o - 8; i < o; i += 2) asm volatile("lop3.b32 %0, %0, %1, %2, 0x80;" : "+r"(keep) : "r"(hp[i]), "r"(hp[i + 1]));
        }
    }
}

__device__ __forceinline__ int pos_of(int n) { return (n & 24) + 4 * (n & 1) + ((n >> 1) & 3); }
__device__ __forceinline__ int unit_of(int role, int u, int& slot) {
    const int g = role & 7, w = (role >> 3) & 3, b = role >> 5;
    slot = role >= 128 ? g : (g ? 16 * g + w + 4 * b : 4 * w + b);
    return role >= 128 ? 32 * max(2 * g + u, 1) : (g ? g + 16 * w : ((w & 1) << 4) + ((w & 2) << 2)) + 64 * b + 256 * u;
}
template <int STRIDE> __device__ __forceinline__ bool tags_ok(uint32_t a, uint32_t ep) {
    uint32_t v[4], ok;
#pragma unroll
    for (int i = 0; i < 4; i++) asm volatile("ld.shared.u32 %0, [%1];" : "=r"(v[i]) : "r"(a + i * STRIDE) : "memory");
    asm volatile("{.reg .pred p; .reg .b32 a, b; lop3.b32 a, %1, %2, %5, 0x7e; lop3.b32 b, %3, %4, %5, 0x7e; lop3.b32 a, a, b, 1, 0xa8;\n"
                 "setp.eq.u32 p, a, 0; vote.sync.all.pred p, p, -1; selp.u32 %0, 1, 0, p;}" : "=r"(ok) : "r"(v[0]), "r"(v[1]), "r"(v[2]), "r"(v[3]), "r"(ep));
    return ok;
}
__device__ __forceinline__ void load_w_rows(uint32_t dst, const CUtensorMap* mr, const CUtensorMap* mi, int kap, uint32_t bar) {
#pragma unroll 1
    for (int i = 0; i < 4; i++) {
        __nanosleep(200);
        if (elect_one()) {
            if (!i) mbar_expect_tx(bar, 16 * WPITCH);
            tma2d(dst + i * 4 * WPITCH, (i & 1) ? mi : mr, ((i < 2 ? kap : (512 - kap) & 511) * 1026 >> 4) * 2, 0, bar);
        }
    }
}
template <int K0, int K1> __device__ __forceinline__ void store_v(const uint32_t (&vo)[32], const uint8_t* vp, bool p) {
    if (p) {
#pragma unroll
        for (int k = K0; k < K1; k++)
            asm volatile("st.global.v2.b32 [%0], {%1,%2};" ::"l"(vp + (k >> 2) * (1 << 20) + ((k >> 1) & 1) * 8192 + (k & 1) * (4 * 32768)), "r"(vo[2 * k]), "r"(vo[2 * k + 1]) : "memory");
    }
}
#define SB0 1024
__device__ __forceinline__ uint64_t ring_desc(uint32_t sb, uint32_t off, uint32_t lbo, uint32_t swz) {
    uint64_t d;
    asm volatile("{.reg .b32 z; shr.u32 z, %1, 28; mov.b64 %0, {z, z}; add.u64 %0, %0, %2;}" : "=l"(d) : "r"(sb), "l"(mkdesc(SB0 + off, lbo, 1024, swz)));
    return d;
}
struct Ring {
    uint32_t full, rel;
    uint32_t n;
    bool sig;
};
__device__ __forceinline__ void ring_release(const Ring& r, uint32_t o) {
    if (r.sig) asm volatile("mbarrier.arrive.shared::cluster.b64 _, [%0];" ::"r"(r.rel + o) : "memory");
}
__device__ __forceinline__ void peek(uint32_t a, uint32_t ph) { asm volatile("mbarrier.test_wait.parity.shared::cta.b64 pk, [%0], %1;" ::"r"(a), "r"(ph) : "memory"); }
__device__ __forceinline__ void peek_wait(uint32_t a, uint32_t ph, uint32_t& n) {
    asm volatile("{@pk bra DONE;\n"
                 "LOOP: mbarrier.try_wait.parity.shared::cta.b64 pk, [%1], %2; add.u32 %0, %0, 1; setp.gt.or.u32 pk, %0, %3, pk; @!pk bra LOOP;\n"
                 "DONE: }" : "+r"(n) : "r"(a), "r"(ph), "n"(SPIN_LIMIT) : "memory");
}
#define SL(k) ((k) % NST)
#define PH(k) (((k) / NST) & 1)
#define H64 "%64,%65,%66,%67,%68,%69,%70,%71,%72,%73,%74,%75,%76,%77,%78,%79,%80,%81,%82,%83,%84,%85,%86,%87,%88,%89,%90,%91,%92,%93,%94,%95," \
            "%96,%97,%98,%99,%100,%101,%102,%103,%104,%105,%106,%107,%108,%109,%110,%111,%112,%113,%114,%115,%116,%117,%118,%119,%120,%121,%122,%123,%124,%125,%126,%127"
#define WG_MMA "wgmma.mma_async.sync.aligned.m64n128k16.f32.bf16.bf16 "
#define DESC_B(S, j) "mov.b64 {t, hb}, %130; mov.b64 db, {%137 + 2048 * " #S " + 2 * " #j ", hb};\n"
#define MMA_LO(S, j, p) "add.u64 da, %129, 2048 * " #S " + %136 * " #j ";" DESC_B(S, j) WG_MMA "{" L64 "}, da, db, " #p ", 1, 1, %138, 0;\n"
#define MMA_HI(S, j, p) "add.u64 da, %129, 2048 * " #S " + 512 + %136 * " #j ";\n" WG_MMA "{" H64 "}, da, db, " #p ", 1, 1, %138, 0;\n"
#define STEP(S, P, N, ph, pa, pr, X, Y) \
    "wgmma.fence.sync.aligned;\n" MMA_LO(S, 0, pa) MMA_HI(S, 0, pa) \
    "wgmma.commit_group.sync.aligned; wgmma.wait_group.sync.aligned 1; @" #pr " mbarrier.arrive.shared::cluster.b64 _, [%132 + 8 * " #P "];\n" MMA_LO(S, 1, 1) \
    "mbarrier.test_wait.parity.shared::cta.b64 pk, [%131 + 8 * " #N "], " #ph ";\n" MMA_HI(S, 1, 1) MMA_LO(S, 2, 1) X MMA_HI(S, 2, 1) MMA_LO(S, 3, 1) MMA_HI(S, 3, 1) \
    "wgmma.commit_group.sync.aligned;\n" P4A Y "@pk bra GO" #S ";\n" \
    "WAIT" #S ": mbarrier.try_wait.parity.shared::cta.b64 pk, [%131 + 8 * " #N "], " #ph "; add.u32 %128, %128, 1; setp.gt.or.u32 pk, %128, %139, pk; @!pk bra WAIT" #S ";\n" \
    "GO" #S ":\n" P4B
#define P4A
#define P4B
#define P4I
#define P4O
#define STEP_ARGS(TA) \
    : R8(d, 0), R8(d, 8), R8(d, 16), R8(d, 24), R8(d, 32), R8(d, 40), R8(d, 48), R8(d, 56), \
      R8(d, 64), R8(d, 72), R8(d, 80), R8(d, 88), R8(d, 96), R8(d, 104), R8(d, 112), R8(d, 120), "+r"(r.n) \
    : "l"(ha), "l"(hb), "r"(r.full), "r"(r.rel), "r"((uint32_t)r.sig), "r"(wg), \
      "n"(SB0 / 16 + (TA ? 32 << 16 : 1 << 16)), "n"(TA ? 128 : 2), "n"(SB0 / 16 + 1024 + (1 << 16)), "n"(TA), "n"(SPIN_LIMIT) P4O \
    : "memory"
#define STEP_REGS "{.reg .b32 k, t, ph, hb; .reg .b64 da, db; .reg .pred ps, pl, pa, pr;\n" P4I "setp.ne.u32 ps, %133, 0;\n"
#define FIRST_WAIT "FIRST: mbarrier.try_wait.parity.shared::cta.b64 pk, [t], ph; @pk bra START; add.u32 %128, %128, 1; setp.le.u32 pk, %128, %139; @pk bra FIRST; START:\n"
__device__ __forceinline__ void gemm1(float (&d)[128], Ring& r, uint64_t ha, uint64_t hb, int wg) {
    asm volatile(STEP_REGS "mul.lo.u32 k, %134, 15; mov.b32 ph, %134; setp.ne.u32 pl, k, 0; mad.lo.u32 t, %134, 8, %131;\n"
                 "pmevent 1; @pl bar.sync 1, 256;\n" FIRST_WAIT "@pl bra ONE;\n"
                 "LOOP: setp.ne.u32 pa, k, 0; and.pred pr, pa, ps; setp.eq.u32 pl, k, 15;\n"
                 STEP(0, 4, 1, ph, pa, pr, "@pl bar.arrive 1, 256;\n", "@pl bra END;\n")
                 "ONE: setp.ne.u32 pa, k, 15; and.pred pr, pa, ps; setp.eq.u32 pl, k, 30;\n"
                 STEP(1, 0, 2, ph, pa, pr, "@pl bar.arrive 2, 256;\n", "@pl bra END;\n")
                 STEP(2, 1, 3, ph, 1, ps, "", "") STEP(3, 2, 4, ph, 1, ps, "", "") "xor.b32 ph, ph, 1; add.u32 k, k, 5;\n" STEP(4, 3, 0, ph, 1, ps, "", "")
                 "bra LOOP;\n"
                 "END:\n" P4B "}" STEP_ARGS(0));
}
__device__ __forceinline__ void gemm2(float (&d)[128], Ring& r, uint64_t ha, uint64_t hb, int wg) {
    asm volatile(STEP_REGS "mov.b32 k, 0; mov.b32 ph, 0; add.u32 t, %131, 16;\n"
                 "pmevent 1; bar.sync 2, 256;\n" FIRST_WAIT
                 "LOOP: setp.ne.u32 pa, k, 0; and.pred pr, pa, ps; setp.eq.u32 pl, k, 5;\n"
                 STEP(2, 1, 3, ph, pa, pr, "", "") STEP(3, 2, 4, ph, 1, ps, "", "") "xor.b32 ph, ph, 1; add.u32 k, k, 1;\n" STEP(4, 3, 0, ph, 1, ps, "", "")
                 "@pl bra END;\n" STEP(0, 4, 1, ph, 1, ps, "", "") STEP(1, 0, 2, ph, 1, ps, "", "")
                 "bra LOOP;\n"
                 "END: }" STEP_ARGS(1));
}
template <int O, int K, int J> __device__ __forceinline__ void mma_h(float (&y)[128], uint64_t a, uint64_t b) { mma128_ss<O, 1, 0>(y, a + SL(K) * 2048 + O * 8 + 128 * J, b + SL(K) * 2048 + 2 * J, 1); }
template <int O, int K> __device__ __forceinline__ void half_step(float (&y)[128], uint64_t a, uint64_t b) { mma_h<O, K, 0>(y, a, b); mma_h<O, K, 1>(y, a, b); mma_h<O, K, 2>(y, a, b); mma_h<O, K, 3>(y, a, b); }
template <int R, int U> __device__ __forceinline__ void out_piece(float (&y)[128], const uint32_t (&dd)[16], uint32_t x0, uint32_t x1, float* op) {
    const int i = 64 * (R >> 1) + 8 * U + 2 * (R & 1);
    asm("mul.rn.bf16x2 %0, %0, %1;" : "+r"(x0) : "r"(dd[2 * U]));
    asm("mul.rn.bf16x2 %0, %0, %1;" : "+r"(x1) : "r"(dd[2 * U + 1]));
    asm volatile("st.global.v4.f32 [%0], {%1,%2,%3,%4};" ::"l"(op + (32 * (R & 1) + 16 * (R >> 1)) * 2048 + 16 * U),
                 "f"(y[i] + __uint_as_float(x0 << 16)), "f"(y[i + 1] + __uint_as_float(x0 & 0xffff0000u)),
                 "f"(y[i + 4] + __uint_as_float(x1 << 16)), "f"(y[i + 5] + __uint_as_float(x1 & 0xffff0000u)) : "memory");
}
template <int R, int U0> __device__ __forceinline__ void load_x4(uint32_t (&xx)[8], uint32_t xa) {
#pragma unroll
    for (int u = 0; u < 4; u++)
        asm volatile("ld.shared.v2.b32 {%0,%1}, [%2];" : "=r"(xx[2 * u]), "=r"(xx[2 * u + 1]) : "r"((xa ^ (u << 5)) + (3 - R) * 8192 + U0 * 1024) : "memory");
}
__device__ __forceinline__ Ring ring_at(uint32_t sb, int k) {
    Ring r;
    r.n = 0;
    r.full = sb + OFF_BAR + B_FULL;
    asm("mapa.shared::cluster.u32 %0, %1, %2;" : "=r"(r.rel) : "r"(sb + OFF_BAR + B_EMPTY), "r"((threadIdx.x >> 5) & 1));
    r.sig = __shfl_sync(~0u, threadIdx.x & 95, threadIdx.x) == 0;
    return r;
}

template <bool BY_SM> __global__ void __cluster_dims__(2, 1, 1) __launch_bounds__(512, 1)
fused_kernel(const __grid_constant__ CUtensorMap tmX, const __grid_constant__ CUtensorMap tmBre, const __grid_constant__ CUtensorMap tmBim,
             const __grid_constant__ CUtensorMap tmCre, const __grid_constant__ CUtensorMap tmCim, const __grid_constant__ CUtensorMap tmXd,
             const __grid_constant__ CUtensorMap tmUst, const __grid_constant__ CUtensorMap tmVst,
             const __grid_constant__ CUtensorMap tmWr, const __grid_constant__ CUtensorMap tmWi, const __grid_constant__ CUtensorMap tmXa,
             const Params p) {
    extern __shared__ __align__(1024) uint8_t smraw[];
    asm volatile(".reg .pred pk, p0;");
    const int tid = threadIdx.x, rank = blockIdx.x & 1;
    const uint32_t wi = __shfl_sync(~0u, smem_u32(smraw) + (tid >> 5), 0), sb = wi & ~15u, bars = sb + OFF_BAR;
    const int wg = (wi >> 2) & 3, w = wi & 3, lane = tid & 31, g = lane >> 2, q = lane & 3;
    if (wg != 3) asm volatile("barrier.cluster.arrive.relaxed.aligned; barrier.cluster.wait.aligned;" ::: "memory");
    else asm volatile("prefetch.tensormap [%0];" ::"l"(w == 0 ? &tmX : w == 1 ? &tmBre : &tmBim) : "memory");
    int role;
    {
        uint32_t T = blockIdx.x;
        if (BY_SM) asm("mov.u32 %0, %%smid;" : "=r"(T));
        T >>= 1;
        const uint32_t a = ((T - 32) * 37) >> 8;
        asm("{.reg .pred p; setp.lt.u32 p, %1, 62; selp.u32 %0, 4, -58, p; add.u32 %0, %0, %1;\n"
            "setp.lt.u32 p, %1, 60; selp.u32 %0, %2, %0, p; setp.lt.u32 p, %1, 32; selp.u32 %0, %3, %0, p;}"
            : "=&r"(role) : "r"(T), "r"(8 * (T - 31 - 7 * a) + 4 + a), "r"(8 * (T & 7) + (T >> 3)));
        role = 2 * role + rank;
    }
    const bool spare = role >= 128;
    const int tc = ((role >> 3) & 14) + rank, cb = (role >> 1) & 7;
    const int fb = role >> 5, fcb = role & 31, fpos = pos_of(fcb);
    const int nu = role == 128 ? 1 : (fcb || !role ? 2 : 0);

    if (wg == 3) {
        if (elect_one()) {
            const uint32_t b = bars + w * 8;
            STAMP5(57);
            mbar_init(b, 1);
            if (w < 3 && !spare) {
                mbar_expect_tx(b, 32768);
                tma5d(sb + w * 32768 + 16384, &tmX, w * 64, 0, 0, 0, tc, b);
                if (w == 0) { tma4d(sb, &tmBre, 0, 0, 0, cb * 4, b); tma4d(sb + 8192, &tmBim, 0, 0, 0, cb * 4, b); }
                STAMP5(58);
            }
#pragma unroll
            for (int o = 32; o < B_EPOCH; o += 32) mbar_init(b + o, o < B_EMPTY ? 1 : (o < B_STG ? 2 : (o < B_P3M ? 4 : 8)));
            asm volatile("fence.mbarrier_init.release.cluster;" ::: "memory");
        }
        __syncwarp();
        STAMP5(59);
        asm volatile("barrier.cluster.arrive.relaxed.aligned;" ::: "memory");
    }
    if (opaque32(wg) == 3) {
        asm volatile("setmaxnreg.dec.sync.aligned.u32 24;");
        asm volatile("barrier.cluster.wait.aligned;" ::: "memory");
        if (w == 0) {
            if (!spare && elect_one()) {
                STAMP(56);
#pragma unroll 1
                for (int k = 1; k < NST; k++) {
                    if (k >= 3) mbar_expect_tx(bars + B_FULL + k * 8, 32768);
                    tma4d_mc(sb + k * 32768 + rank * 8192, rank ? &tmBim : &tmBre, k * 64, 0, 0, cb * 4, bars + B_FULL + k * 8);
                    if (k >= 3) tma5d(sb + k * 32768 + 16384, &tmX, k * 64, 0, 0, 0, tc, bars + B_FULL + k * 8);
                }
#define RING_WAIT "mbarrier.try_wait.parity.shared::cta.b64 p, [fb + 256], ph; @p bra GO;\n" \
                  "WAIT: mbarrier.try_wait.parity.shared::cta.b64 p, [fb + 256], ph; add.u32 n, n, 1; setp.gt.or.u32 p, n, 32768, p; @!p bra WAIT;\nGO:\n"
#define RING_NEXT "pmevent 1; add.u32 o, o, 8; setp.eq.u32 p, o, 40; selp.u32 o, 0, o, p; @p xor.b32 ph, ph, 1; add.u32 fb, %1, o; shl.b32 t, o, 12; add.u32 da, %0, t;\n"
                asm volatile("{.reg .b32 o, k, kk, c2, da, db, fb, ph, n, t; .reg .pred p;\n"
                             "mov.b32 o, 0; mov.b32 k, 320; mov.b32 kk, 320; mov.b32 c2, 0; mov.b32 ph, 0; mov.b32 n, 0; mov.b32 fb, %1; mov.b32 da, %0; mov.b32 db, %2;\n"
                             "LOOP:\n" RING_WAIT
                             "cp.async.bulk.tensor.5d.shared::cluster.global.mbarrier::complete_tx::bytes [da], [%3, {kk,0,0,0,%5}], [fb];\n"
                             "cp.async.bulk.tensor.4d.shared::cluster.global.mbarrier::complete_tx::bytes.multicast::cluster [db], [%4, {kk,0,c2,%6}], [fb], %7;\n"
                             "mbarrier.arrive.expect_tx.shared::cta.b64 _, [fb], 32768;\n" RING_NEXT
                             "add.u32 db, %2, t; add.u32 k, k, 64; and.b32 kk, k, 1023; shr.u32 c2, k, 9; and.b32 c2, c2, 2; setp.ne.u32 p, k, 2048; @p bra LOOP;}"
                             ::"r"(sb + 16384), "r"(bars + B_FULL), "r"(sb + rank * 8192), "l"(&tmX), "l"(rank ? &tmBim : &tmBre), "r"(tc), "r"(cb * 4), "h"((uint16_t)3) : "memory");
                asm volatile("{.reg .b32 o, k, kk, da, db, fb, hb, ph, n, t; .reg .b64 m, src; .reg .pred p;\n"
                             "mov.b32 o, 16; mov.b32 k, 0; mov.b32 kk, 0; mov.b32 ph, 1; mov.b32 n, 0; add.u32 fb, %1, 16; add.u32 hb, %1, 72; add.u32 da, %0, 65536; add.u32 db, %2, 65536;\n"
                             "mov.b64 m, %3; mov.b64 src, %5;\n"
                             "GROUP: add.u32 t, %8, k;\n"
                             "OWN: mbarrier.try_wait.parity.shared::cta.b64 p, [t], 0; add.u32 n, n, 1; setp.gt.or.u32 p, n, 32768, p; @!p bra OWN;\n"
                             "LOOP:\n" RING_WAIT
                             "cp.async.bulk.shared::cluster.global.mbarrier::complete_tx::bytes [da], [src], 16384, [hb];\n"
                             "cp.async.bulk.tensor.5d.shared::cluster.global.mbarrier::complete_tx::bytes.multicast::cluster [db], [m, {kk,0,0,0,%6}], [fb], %7;\n"
                             "mbarrier.expect_tx.shared::cta.b64 [fb], 16384; mbarrier.arrive.expect_tx.shared::cta.b64 _, [hb], 16384;\n" RING_NEXT
                             "add.u32 db, %2, t; add.u64 src, src, 16384; sub.u64 m, %4, m; add.u32 k, k, 1; shl.b32 kk, k, 5; and.b32 kk, kk, 0x7c0;\n"
                             "and.b32 t, k, 1; mad.lo.u32 hb, t, 8, fb; add.u32 hb, hb, o; add.u32 hb, hb, 40;\n"
                             "and.b32 t, k, 7; setp.ne.u32 p, t, 0; @p bra LOOP; setp.ne.u32 p, k, 32; @p bra GROUP;}"
                             ::"r"(sb), "r"(bars + B_FULL), "r"(sb + 16384 + rank * 8192), "l"(&tmCre), "l"((uint64_t)&tmCre + (uint64_t)&tmCim),
                               "l"(g_H + (size_t)tc * 32 * 16384), "r"(cb * 8 + rank * 4), "h"((uint16_t)3), "r"(bars + B_HOWN) : "memory");
            }
        } else if (opaque32(w) == 1) {
            const unsigned ep = ld_rlx(g_epoch + role * 8) + 1;
            __syncwarp();
            if (elect_one()) {
                asm volatile("st.relaxed.gpu.global.u32 [%0], %1;" ::"l"(g_epoch + role * 8), "r"(ep) : "memory");
                asm volatile("st.shared.u32 [%0], %1;" ::"r"(bars + B_EPOCH), "r"(ep) : "memory");
                mbar_arrive(bars + B_EP);
            }
            int slot;
            const int kap1 = unit_of(role, 1, slot);
            uint32_t lph = 0;
            if (!spare) mbar_wait(bars + B_STGU, 0);
            STAMP(21);
            const int c0 = fb * 2048 + fpos * 64;
            if (elect_one()) {
                if (!spare) {
#pragma unroll 1
                    for (int r = 4; r < 8; r++) bulk_st(g_X + r * (32 * 16384) + c0 * 2, sb + OFF_P + r * 4096, 128);
                    tma2d_st(&tmUst, c0, 0, sb + OFF_P);
                    bulk_commit();
                    tma2d_st(&tmUst, c0, 64, sb + OFF_P + 8192);
                    bulk_commit();
                    asm volatile("cp.async.bulk.wait_group.read 1;" ::: "memory");
                    red_hint(g_cnt);
                }
            }
            STAMP(40);
#pragma unroll 1
            for (int e = 0; e < 4; e++) {
                if (e >= 2) {
                    if (e == nu) {
                        mbar_wait(bars + B_WFREE, !spare);
                        load_w_rows(sb + OFF_WD, &tmWr, &tmWi, kap1, bars + B_WD);
                    }
                    if (e - 2 < nu) mbar_wait(bars + B_STG, e & 1);
                    STAMPO(23, e - 2);
                    if (e == nu && elect_one()) {
                        const int c = (role ? slot : 256) * 32;
                        tma2d_st(&tmVst, c, 0, sb + OFF_P);
                        tma2d_st(&tmVst, c + 4096, 0, sb + OFF_P + 8192);
                        bulk_commit();
                        if (role) { bulk_wait_read(); red_hint(g_cnt + 64); } else bulk_wait_all();
                    }
                    if (e == 3 && !spare && elect_one()) {
                        mbar_expect_tx(bars + B_FG, 8192);
                        bulk_ld(sb + OFF_F, (const uint8_t*)g_tab + TAB_G + fb * 8192, 8192, bars + B_FG);
                    }
                }
                const uint32_t tg = e < 2 ? lane * 128 + ((((lane >> 1) & 2) ^ (lane & 3)) << 4) + (lane >> 3) * 4 : lane * 64 + (lane & 8) * 4 + (lane & 2) * 8 + (lane & 4) * 2;
                if (spare) {
                    if (e == 1) {
                        wait_cnt(g_cnt, 128 * ep);
                        STAMP(42);
#pragma unroll 1
                        for (int n = 0; n < 4096; n++) {
                            if (elect_one()) {
                                mbar_expect_tx(bars + B_LD, 8 * 16384);
#pragma unroll 1
                                for (int r = 0; r < 8; r++) bulk_ld(sb + r * 16384, g_X + (size_t)r * (32 * 16384), 16384, bars + B_LD);
                            }
                            mbar_wait(bars + B_LD, n & 1);
                            bool ok = true;
#pragma unroll 1
                            for (int r = 0; r < 8; r++) ok &= tags_ok<4096>(sb + r * 16384 + tg, ep);
                            if (ok) break;
                        }
                        if (elect_one()) mbar_arrive(bars + B_RAW);
                    }
                } else {
                    const uint32_t dst = sb + OFF_P + (e & 1) * 16384;
#define X_ST1
#define X_ST2
#define X_RETRY
#define X_ARG
                    asm volatile("{.reg .b32 n, a, v0, v1, v2, v3; .reg .pred p, pe, pu;\n"
                                 "elect.sync _|pe, 0xffffffff; setp.lt.u32 pu, %10, 2; mov.b32 n, 0; pmevent 1;\n"
                                 "POLL: ld.relaxed.gpu.global.u32 v0, [%1]; setp.eq.u32 p, v0, %2; @p bra LOAD;\n"
                                 "nanosleep.u32 20; add.u32 n, n, 1; setp.lt.u32 p, n, 32768; @p bra POLL;\n"
                                 "LOAD:\n" X_ST1 "cp.async.bulk.wait_group.read 0;\n"
                                 "@pe cp.async.bulk.shared::cluster.global.mbarrier::complete_tx::bytes [%3], [%4], 16384, [%5]; @pe mbarrier.arrive.expect_tx.shared::cta.b64 _, [%5], 16384;\n"
                                 "mov.b32 a, 0;\n"
                                 "WAIT: mbarrier.try_wait.parity.shared::cta.b64 p, [%5], %0; @p bra CHECK; add.u32 n, n, 1; setp.lt.u32 p, n, 65536; @p bra WAIT;\n"
                                 "CHECK:\n" X_ST2 "@pu bra FOUR;\n"
                                 "ld.shared.u32 a, [%7]; ld.shared.u32 v0, [%6 + 2048]; ld.shared.u32 v1, [%6 + 6144]; ld.shared.u32 v2, [%6 + 10240]; ld.shared.u32 v3, [%6 + 14336];\n"
                                 "lop3.b32 a, a, v0, %8, 0x7e; lop3.b32 v1, v1, v2, %8, 0x7e; lop3.b32 a, a, v3, %8, 0xf6; or.b32 a, a, v1;\n"
                                 "FOUR: ld.shared.u32 v0, [%6]; ld.shared.u32 v1, [%6 + 4096]; ld.shared.u32 v2, [%6 + 8192]; ld.shared.u32 v3, [%6 + 12288];\n"
                                 "lop3.b32 a, a, v0, %8, 0xf6; lop3.b32 a, a, v1, %8, 0xf6; lop3.b32 v2, v2, v3, %8, 0x7e; lop3.b32 a, a, v2, 1, 0xa8;\n"
                                 "setp.eq.u32 p, a, 0; vote.sync.all.pred p, p, -1; @p bra OK;\n" X_RETRY
                                 "add.u32 n, n, 16; setp.ge.u32 p, n, 65536; @p bra OK; xor.b32 %0, %0, 1; bra LOAD;\n"
                                 "OK: @pe mbarrier.arrive.shared::cta.b64 _, [%9]; pmevent 1; xor.b32 %0, %0, 1;}"
                                 : "+r"(lph)
                                 : "l"(g_cnt + e * 32), "r"(128 * ep), "r"(dst), "l"(g_X + (size_t)(e < 2 ? role + e * 128 : 254 + (fb * 32 + fpos) * 2 + e) * 16384), "r"(bars + B_LD),
                                   "r"(dst + tg), "r"(dst + (e == 3 ? (lane & 1) * 8192 + 32 : 0)), "r"(ep), "r"(bars + B_IN + e * 8), "r"(e) X_ARG : "memory");
                }
                if (e == 0 && !spare && elect_one()) {
                    tma2d_st(&tmUst, c0, 128, sb + OFF_P + 16384);
                    tma2d_st(&tmUst, c0, 192, sb + OFF_P + 24576);
                    bulk_commit();
                    bulk_wait_read();
                    red_hint(g_cnt + 32);
                }
            }
            if (!spare) {
                mbar_wait(bars + B_HOWN + 8, 0);
#pragma unroll 1
                for (int r = 0; r < 4; r++) {
                    if (r == 3) mbar_wait(bars + B_P3M, 0);
                    if (elect_one()) {
                        if (r == 0) { mbar_expect_tx(bars + B_XD, 24576 + 256); mbar_expect_tx(bars + B_XD + 8, 8192); bulk_ld(sb + OFF_LAM, p.dsk + cb * 128, 256, bars + B_XD); }
                        tma4d(sb + OFF_F + (3 - r) * 8192, &tmXd, 0, tc * 128 + 32 * (r & 1) + 16 * (r >> 1), 0, cb * 2, bars + B_XD + (r == 3) * 8);
                    }
                    __nanosleep(PACE_X);
                }
            }
        } else {
            if (w == 2) {
                {
                    const int u = lane >> 4;
                    int slot;
                    const int r0 = unit_of(role, u, slot) + 512 * ((lane >> 1) & 3), r1 = (2048 - r0) & 2047, mir = (lane >> 3) & 1;
                    const unsigned short* wp = (const unsigned short*)((lane & 1) ? p.wi : p.wr);
                    const float a = bf2f(wp[r0 * 513 + mir * 512]), b = bf2f(wp[r1 * 513 + mir * 512]);
                    asm volatile("st.shared.f32 [%0], %1;" ::"r"(sb + OFF_WSP + u * 64 + (lane & 15) * 4), "f"(0.5f * ((lane & 1) ? (mir ? b - a : a - b) : a + b)) : "memory");
                }
                warp_arrive(bars + B_WSP);
                int slot;
                const int kap = unit_of(role, 0, slot);
                if (!spare) mbar_wait(bars + B_WFREE, 0);
                if (elect_one()) {
                    mbar_expect_tx(bars + B_FG, 8192);
                    bulk_ld(sb + OFF_F, (const uint8_t*)g_tab + TAB_FG, 8192, bars + B_FG);
                }
                if (nu) load_w_rows(sb + OFF_WD, &tmWr, &tmWi, kap, bars + B_WD);
            } else if (!spare) {
#pragma unroll 1
                for (int i = 0; i < 8; i++) {
                    if (i >= XA_N0) __nanosleep(XA_PACE);
                    if (elect_one()) {
                        const uint32_t xb = bars + (i < 4 ? B_RAW : B_XIN);
                        if (!(i & 3)) mbar_expect_tx(xb, 16384);
                        tma3d(sb + OFF_F + i * 4096, &tmXa, fcb * 32, 0, 4 * i + fb, xb);
                    }
                }
            }
            if (!spare) {
                const unsigned ep = get_epoch(bars);
#define CNT_RETRY
#define CNT_ARG
                asm volatile("{.reg .b32 o, k, hb, fb, ca, m, ph, rph, n, t, v0, v1, v2, v3; .reg .b64 src; .reg .pred p, pe;\n"
                             "elect.sync _|pe, 0xffffffff; mov.b32 o, %0; shr.u32 k, %0, 3; sub.u32 k, k, 2; mov.b32 m, 0x107c0; mov.b32 rph, 0; mov.b32 n, 0;\n"
                             "bra NEXT;\n"
                             "LOOP: mbarrier.try_wait.parity.shared::cta.b64 p, [hb], ph; @p bra GO;\n"
                             "WAIT: mbarrier.try_wait.parity.shared::cta.b64 p, [hb], ph; add.u32 n, n, 1; setp.gt.or.u32 p, n, 32768, p; @!p bra WAIT;\n"
                             "GO: ld.shared.u32 v0, [ca]; ld.shared.u32 v1, [ca + 128]; ld.shared.u32 v2, [ca + 256]; ld.shared.u32 v3, [ca + 384];\n"
                             "lop3.b32 v0, v0, v1, %4, 0x7e; lop3.b32 v2, v2, v3, %4, 0x7e; lop3.b32 v0, v0, v2, 1, 0xa8; setp.eq.u32 p, v0, 0; vote.sync.all.pred p, p, -1; @p bra OK;\n"
                             CNT_RETRY "add.u32 n, n, 16; setp.gt.u32 p, n, 32768; @p bra OK;\n"
                             "shl.b32 t, o, 12; add.u32 t, t, %5; mad.wide.u32 src, k, 16384, %6;\n"
                             "@pe mbarrier.arrive.expect_tx.shared::cta.b64 _, [%7], 16384; @pe cp.async.bulk.shared::cluster.global.mbarrier::complete_tx::bytes [t], [src], 16384, [%7];\n"
                             "AGAIN: mbarrier.try_wait.parity.shared::cta.b64 p, [%7], rph; add.u32 n, n, 1; setp.gt.or.u32 p, n, 32768, p; @!p bra AGAIN;\n"
                             "xor.b32 rph, rph, 1; bra GO;\n"
                             "OK: @pe mbarrier.arrive.shared::cta.b64 _, [fb]; pmevent 1;\n"
                             "add.u32 o, o, 16; setp.ge.u32 p, o, 40; @p sub.u32 o, o, 40; add.u32 k, k, 2;\n"
                             "NEXT: shr.u32 m, m, 1; and.b32 ph, m, 1; add.u32 fb, %1, o; mad.lo.u32 hb, o, 2, %2; mad.lo.u32 ca, o, 4096, %3; setp.lt.u32 p, k, 32; @p bra LOOP;}"
                             ::"r"(8 * w), "r"(bars + B_FULL), "r"(bars + B_HL - 16 + w * 8), "r"(sb + (q >> 1) * 8192 + (q & 1) * 512 + g * 1040 + q * 4), "r"(ep),
                               "r"(sb), "l"(g_H + (size_t)tc * 32 * 16384), "r"(bars + B_HR - 16 + w * 8) CNT_ARG : "memory");
                if (w == 3) warp_arrive(bars + B_DONE);
            }
        }
    } else {
        STAMP(55);
        asm volatile("setmaxnreg.inc.sync.aligned.u32 152;");
        STAMP5(60);
        const int t7 = tid & 127, hf = wg - 1;
        const int mi = lane >> 3, gl = lane & 7;
        if (spare && wg != 2) {
            if (tid < 64) { const uint4 v = __ldg((const uint4*)((const uint8_t*)g_tab + TAB_PC) + tid); sts128(sb + OFF_LAM + tid * 16, v.x, v.y, v.z, v.w); }
            bar_sync(1, 256);
            mbar_wait(bars + B_RAW, 0);
            STAMP(0);
#pragma unroll 1
            for (int u = 0; u < nu; u++) {
                int slot;
                const int t = unit_of(role, u, slot) >> 5;
                const uint32_t off = (tid >> 2) * 128 + q * 16;
                float zr[16], zi[16];
#pragma unroll
                for (int k = 0; k < 16; k++) zr[k] = zi[k] = 0.f;
#pragma unroll 1
                for (int r = (t & 1) ? 0 : t >> 1; r < 8 - ((t & 1) ? 0 : (t >> 1) - 1); r += (t & 1) ? 1 : 8 - t) {
                    float4 c;
                    float a[8], b[8];
                    lds128f(sb + OFF_LAM + t * 128 + r * 16, c.x, c.y, c.z, c.w);
                    lds128f(sb + r * 16384 + off, a[0], a[1], a[2], a[3]);
                    lds128f(sb + r * 16384 + off + 64, b[0], b[1], b[2], b[3]);
                    lds128f(sb + r * 16384 + off + 8192, a[4], a[5], a[6], a[7]);
                    lds128f(sb + r * 16384 + off + 8192 + 64, b[4], b[5], b[6], b[7]);
#pragma unroll
                    for (int k = 0; k < 16; k++) {
                        const uint32_t ua = __float_as_uint(a[k >> 1]), ub = __float_as_uint(b[k >> 1]);
                        const float x = __uint_as_float((k & 1) ? ua & 0xffff0000u : ua << 16), y = __uint_as_float((k & 1) ? ub & 0xffff0000u : ub << 16);
                        zr[k] = fmaf(c.x, x, fmaf(c.z, y, zr[k]));
                        zi[k] = fmaf(c.y, x, fmaf(c.w, y, zi[k]));
                    }
                }
                const uint32_t dst = sb + OFF_P + u * 16384 + off;
#pragma unroll
                for (int k = 0; k < 16; k += 8) {
                    sts128(dst + k * 1024, pk(zr[k], zr[k + 1]), pk(zr[k + 2], zr[k + 3]), pk(zr[k + 4], zr[k + 5]), pk(zr[k + 6], zr[k + 7]));
                    sts128(dst + k * 1024 + 64, pk(zi[k], zi[k + 1]), pk(zi[k + 2], zi[k + 3]), pk(zi[k + 4], zi[k + 5]), pk(zi[k + 6], zi[k + 7]));
                }
                fence_async_sm();
                bar_sync(1, 256);
                if (tid == 0) mbar_arrive(bars + B_IN + u * 8);
                STAMPO(1, u);
            }
            return;
        }
        if (wg == 2 && !spare) {
            asm volatile("setmaxnreg.inc.sync.aligned.u32 176;");
            uint32_t f1[16];
            cf tw[8];
            if (TAB_T0) __nanosleep(TAB_T0);
            ldtab<4, 2048>(f1, TAB_F1 + t7 * 16);
            ldtab_cf<16>(tw, TAB_TW1 + (t7 >> 2) * 64);
            const uint32_t ep = get_epoch(bars);
            uint32_t a0 = sb + OFF_P + (8 * w + gl + 32 * (mi >> 1)) * 128 + (((((mi & 1) << 2) | (fpos & 3)) ^ gl) << 4);
            float acc[128];
            const uint64_t dx = opaque(mkdesc(sb + OFF_F, 4096, 512, 2));
            mbar_wait(bars + B_RAW, 0);
            pinu(f1);
            wg_fence();
#pragma unroll
            for (int j = 0; j < 4; j++) mma128_rs<0, 1>(acc, f1[4 * j], f1[4 * j + 1], f1[4 * j + 2], f1[4 * j + 3], dx + j * 64, j);
            wg_commit();
            mbar_wait(bars + B_XIN, 0);
            wg_fence();
            STAMP(20);
#pragma unroll
            for (int j = 0; j < 4; j++) mma128_rs<64, 1>(acc, f1[4 * j], f1[4 * j + 1], f1[4 * j + 2], f1[4 * j + 3], dx + 1024 + j * 64, j);
            wg_commit();
            wg_wait<0>();
            pin(acc);
            pinu(f1);
            warp_arrive(bars + B_WFREE);
#pragma unroll 1
            for (int h = 0;; h++) {
                const uint32_t tmask = 2 * q + h == fpos >> 2 ? ~1u : ~0u, tbit = ep & ~tmask;
#pragma unroll
                for (int cl = 0; cl < 2; cl++) {
                    c2 v[8];
#pragma unroll
                    for (int n = 0; n < 8; n++) {
                        const int i = 4 * (4 * n + cl);
                        v[n] = {{acc[i], acc[i + 2]}, {acc[i + 1], acc[i + 3]}};
                    }
                    dft8<true, YP1>(v, tw);
#pragma unroll
                    for (int r = 0; r < 8; r += 2) {
                        uint32_t o0 = pk(v[r].a.x, v[r].b.x), o1 = pk(v[r].a.y, v[r].b.y), o2 = pk(v[r + 1].a.x, v[r + 1].b.x), o3 = pk(v[r + 1].a.y, v[r + 1].b.y);
                        if (cl == 0) { o0 = (o0 & tmask) | tbit; o2 = (o2 & tmask) | tbit; }
                        stsm4((a0 ^ (cl << 4)) + r * 4096, o0, o1, o2, o3);
                    }
                }
                if (h) break;
                a0 ^= 32;
#pragma unroll
                for (int n = 0; n < 8; n++) {
                    asm volatile("mov.b32 %0, %8; mov.b32 %1, %9; mov.b32 %2, %10; mov.b32 %3, %11; mov.b32 %4, %12; mov.b32 %5, %13; mov.b32 %6, %14; mov.b32 %7, %15; pmevent 1;"
                                 : "=&f"(acc[16 * n]), "=&f"(acc[16 * n + 1]), "=&f"(acc[16 * n + 2]), "=&f"(acc[16 * n + 3]), "=&f"(acc[16 * n + 4]), "=&f"(acc[16 * n + 5]), "=&f"(acc[16 * n + 6]), "=&f"(acc[16 * n + 7])
                                 : "f"(acc[16 * n + 8]), "f"(acc[16 * n + 9]), "f"(acc[16 * n + 10]), "f"(acc[16 * n + 11]), "f"(acc[16 * n + 12]), "f"(acc[16 * n + 13]), "f"(acc[16 * n + 14]), "f"(acc[16 * n + 15]));
                }
            }
            fence_async_sm();
            warp_arrive(bars + B_STGU);
            bar_sync(3, 128);
            asm volatile("setmaxnreg.dec.sync.aligned.u32 152;");
            bar_arrive(7, 256);
        }
        if (wg == 1) {
            if (LAM_T0) __nanosleep(LAM_T0);
            const int cl = tid & 127, ch = (cl >> 6) * 512 + ((cl >> 3) & 1) * 256 + cb * 32 + ((cl >> 4) & 3) * 8 + (cl & 7);
            const float lr = bf2f(*(const unsigned short*)padd(p.lre, 2 * ch)), li = bf2f(*(const unsigned short*)padd(p.lim, 2 * ch));
            const float dt = __bfloat162float(__float2bfloat16(expf(bf2f(*(const unsigned short*)padd(p.ldt, 2 * ch)))));
            const float an = dt * li, th = an * 0.318309873342514f;
            float sn, cs, inv;
            sincospif(fmaf(rintf(0.5f * th), -2.f, th) + fmaf(an, 1.2841276653e-8f, fmaf(an, 0.318309873342514f, -th)), &sn, &cs);
            const float ex = expf(dt * lr), br = ex * cs, bi = ex * sn;
            asm("rcp.approx.f32 %0, %1;" : "=f"(inv) : "f"(lr * lr + li * li));
            inv += inv;
            const float cr = ((br - 1.f) * lr + bi * li) * inv, ci = (bi * lr - (br - 1.f) * li) * inv;
            sts128(sb + OFF_LAM + cl * 16, __float_as_uint(br), __float_as_uint(-bi), __float_as_uint(cr), __float_as_uint(-ci));
            mbar_wait(bars + B_EP, 0);
            bar_sync(8, 128);
            if (tid == 128) mbar_arrive(bars + B_LAM);
        }
        if (wg != 2) {
        if (wg == 0) bar_sync(4, 128); else bar_sync(7, 256);
        asm volatile("setmaxnreg.inc.sync.aligned.u32 160;");
        if (wg == 0) bar_sync(4, 128);
        float d[128];
        STAMPW(0, 10);
        Ring rg = ring_at(sb, role * 66 + wg * 16);
        cf lam[2];
        unsigned ep;
        gemm1(d, rg, ring_desc(sb, 0, 16, 1), ring_desc(sb, 16384, 16, 1), wg);
        const uint32_t lama = sb + OFF_LAM + wg * 1024 + w * 256 + (fresh_lane() & 28) * 4;
        mbar_wait_fast(bars + B_LAM, 0);
        lam[0] = lds_cf(lama); lam[1] = lds_cf(lama + 128);
        asm volatile("ld.shared.u32 %0, [%1];" : "=r"(ep) : "r"(bars + B_EPOCH) : "memory");
        asm volatile("setmaxnreg.inc.sync.aligned.u32 176;");
        cf L[2] = {lam[0], lam[1]};
#pragma unroll
        for (int i = 0; i < 4; i++) { L[0] = csq(L[0]); L[1] = csq(L[1]); }
        asm volatile("" : "+f"(L[0].x), "+f"(L[0].y), "+f"(L[1].x), "+f"(L[1].y)::"memory");
        wg_wait<0>();
        ring_release(rg, 8 * wg);
        pin(d);
        STAMPW(1, 11);
        {
            const int lane = fresh_lane(), g = lane >> 2, q = lane & 3, mi = lane >> 3, gl = lane & 7;
            cf f[2], fb2[2];
#pragma unroll
            for (int i = 0; i < 17; i++) {
#pragma unroll
                for (int h = 0; h < 2; h++) {
                    const int r = 4 * (i >> 1) + 2 * h + (i & 1), r2 = 32 + 4 * ((i - 1) >> 1) + 2 * h + ((i - 1) & 1);
                    if (i < 16) f[h] = i ? cfma(lam[h], f[h], {d[r], -d[64 + r]}) : cf{d[r], -d[64 + r]};
                    if (i > 0) fb2[h] = i > 1 ? cfma(lam[h], fb2[h], {d[r2], -d[64 + r2]}) : cf{d[r2], -d[64 + r2]};
                    if (i && (h || !(YS & 8))) YIELD_S1();
                }
            }
            const uint8_t* cbase = (const uint8_t*)g_carry + (tc * 16 + wg * 8 + cb) * 512 + w * 64;
            const uint8_t* cptr = padd(cbase, g * 8);
            const unsigned tag = ep & 15u;
#pragma unroll
            for (int h = 0; h < 2; h++) { f[h] = cfma(L[h], f[h], fb2[h]); L[h] = csq(L[h]); }
            cf s0[2], s1[2], s2[2];
#pragma unroll
            for (int h = 0; h < 2; h++) {
                s0[h] = {__shfl_sync(~0u, f[h].x, 0, 4), __shfl_sync(~0u, f[h].y, 0, 4)};
                s1[h] = {__shfl_sync(~0u, f[h].x, 1, 4), __shfl_sync(~0u, f[h].y, 1, 4)};
                s2[h] = {__shfl_sync(~0u, f[h].x, 2, 4), __shfl_sync(~0u, f[h].y, 2, 4)};
            }
#pragma unroll
            for (int h = 0; h < 2; h++) {
                s1[h] = cfma(L[h], s0[h], s1[h]);
                s2[h] = cfma(L[h], s1[h], s2[h]);
                f[h] = cfma(L[h], s2[h], f[h]);
                asm volatile("{.reg .pred p; .reg .b64 a; setp.eq.u32 p, %3, 3; mov.b64 a, {%1,%2}; @p st.relaxed.gpu.global.b64 [%0], a;}" ::"l"(cptr + h * 256),
                             "r"((__float_as_uint(f[h].x) & ~15u) | tag), "f"(f[h].y), "r"(q) : "memory");
            }
            STAMPX(2, 12);
            cf gam = lds_cf(lama + 8);
            cf st = csel(q & 2, csel(q & 1, s2[0], s1[0]), csel(q & 1, s0[0], {0.f, 0.f}));
            const cf st1 = csel(q & 2, csel(q & 1, s2[1], s1[1]), csel(q & 1, s0[1], {0.f, 0.f}));
            cptr = padd(cbase - 4 * 8192, (3 - mi) * 8192 + gl * 8);
            const int nprev = tc - 1 - mi;
            const uint8_t* hptr = padd(g_H + (size_t)(tc * 32 + wg * 16 + (cb & 6)) * 16384 + ((cb & 1) * 4 + w) * 1024, g * 64 + ((q ^ (g >> 1)) << 4));
            const uint32_t hm = 4 * (g & 1) + (q ^ (g >> 1)) == (cb & 1) * 4 + w ? ~1u : ~0u;
            float u[64];
            uint64_t fv[4] = {tag, tag, tag, tag};
            prescale<0>(u, d, gam);
            gather(fv, cptr, nprev);
#pragma unroll 1
            for (int h = 0;; h++) {
                const cf L2 = csq(L[0]), M = csq(L2);
                cf M4 = csq(csq(M));
                M4 = {__shfl_sync(~0u, M4.x, 4 * gl), __shfl_sync(~0u, M4.y, 4 * gl)};
                cf lq = cmul(gam, cmul(csel(q & 1, L[0], {1.f, 0.f}), csel(q & 2, L2, {1.f, 0.f})));
                st = cmul(gam, st);
                asm volatile("pmevent 1;" : "+f"(lq.x), "+f"(lq.y), "+f"(st.x), "+f"(st.y));
#pragma unroll 1
                for (unsigned n = 0; __any_sync(~0u, (((uint32_t)fv[0] ^ tag) | ((uint32_t)fv[1] ^ tag) | ((uint32_t)fv[2] ^ tag) | ((uint32_t)fv[3] ^ tag)) & 15u) && n < SPIN_LIMIT; n++) gather(fv, cptr, nprev);
                if (!h) STAMPX(53, 54);
                cf P = as_cf(fv[3]), pj[4];
#pragma unroll
                for (int a = 2; a >= 0; a--) P = cfma(M4, P, as_cf(fv[a]));
                cptr += 256;
                asm volatile("" : "+f"(P.x), "+f"(P.y)::"memory");
                gather(fv, cptr, h ? -1 : nprev);
#pragma unroll
                for (int j = 3; j >= 0; j--) pj[j] = {__shfl_sync(~0u, P.x, g + 8 * j), __shfl_sync(~0u, P.y, g + 8 * j)};
                st = cfma(lq, cfma(M, cfma(M, cfma(M, pj[3], pj[2]), pj[1]), pj[0]), st);
                if (!h) STAMPX(3, 13);
                uint32_t keep = sb >> 28;
                scan2(u, lam[0], st, hptr, hm, ep & ~hm, keep);
                warp_arrive(bars + B_HOWN + wg * 16 + h * 8 + keep);
                if (h) break;
                STAMPW(4, 14);
                if (wg == 1 && nu) bar_sync(9, 256);
                lds128f(lama + 128, lam[0].x, lam[0].y, gam.x, gam.y);
                st = st1;
                L[0] = L[1];
                hptr += 8 * 16384;
                prescale<1>(u, d, gam);
            }
            STAMPW(5, 15);
        }
        if (wg == 0) bar_sync(4, 128); else bar_sync(8, 128);
        if (wg == 0) {
            asm volatile("setmaxnreg.dec.sync.aligned.u32 160;");
            float y[128];
            rg = ring_at(sb, role * 66 + 32);
            STAMP(6);
            STAMP(7);
            const uint64_t dA = ring_desc(sb, 0, 512, 2), dB = ring_desc(sb, 16384, 16, 1);
            gemm2(y, rg, dA, dB, 0);
            asm volatile("setmaxnreg.inc.sync.aligned.u32 184;");
            const int lane = fresh_lane(), g = lane >> 2, q = lane & 3;
            const int pg = 2 * (g & 3) + (g >> 2);
            float* op = (float*)padd(p.out + (size_t)(tc * 128 + 64 * (w & 1) + 8 * (w >> 1)) * 2048 + 1024 + cb * 128, pg * 8192 + q * 16);
            const uint32_t xa = sb + OFF_F + (16 * (w & 1) + 8 * (w >> 1) + pg) * 128 + (((q >> 1) ^ pg) << 4) + (q & 1) * 8;
#define HALF0(k) wg_fence(); peek(k < 63 ? rg.full + SL(k + 1) * 8 : bars + B_XD, PH(k + 1)); half_step<0, k>(y, dA, dB); wg_commit(); peek_wait(k < 63 ? rg.full + SL(k + 1) * 8 : bars + B_XD, PH(k + 1), rg.n);
            HALF0(60) HALF0(61) HALF0(62) HALF0(63)
            const uint64_t dB2 = ring_desc(sb >> 1, 16384, 16, 1);
            uint32_t xa0[8], xa1[8], dd[16];
#pragma unroll
            for (int i = 0; i < 8; i++) asm volatile("ld.shared.v2.b32 {%0,%1}, [%2];" : "=r"(dd[2 * i]), "=r"(dd[2 * i + 1]) : "r"(sb + OFF_LAM + q * 8 + 32 * i) : "memory");
            load_x4<0, 0>(xa0, xa);
            wg_fence();
            half_step<64, 64 - SKEW>(y, dA, dB2);
            wg_commit();
            wg_wait<1>();
#pragma unroll
            for (int i = 0; i < 64; i++) asm volatile("" : "+f"(y[i])::"memory");
            STAMP(16);
#define MM(n) if (4 + (n) < 4 * SKEW) { wg_fence(); mma_h<64, 65 - SKEW + (n) / 4, (n) % 4>(y, dA, dB2); mma_h<64, 65 - SKEW + (n) / 4, (n) % 4 + 1>(y, dA, dB2); }
#define OUT4(R, U, X, n) out_piece<R, U>(y, dd, X[0], X[1], op); MM(n) out_piece<R, U + 1>(y, dd, X[2], X[3], op); MM(n + 2) \
                         out_piece<R, U + 2>(y, dd, X[4], X[5], op); MM(n + 4) out_piece<R, U + 3>(y, dd, X[6], X[7], op); MM(n + 6)
            load_x4<0, 4>(xa1, xa);
            OUT4(0, 0, xa0, 0)
            load_x4<1, 0>(xa0, xa);
            OUT4(0, 4, xa1, 8)
            wg_commit();
            load_x4<1, 4>(xa1, xa);
            OUT4(1, 0, xa0, 16)
            load_x4<2, 0>(xa0, xa);
            OUT4(1, 4, xa1, 16)
            STAMP(18);
            wg_wait<0>();
#pragma unroll
            for (int i = 64; i < 128; i++) asm volatile("" : "+f"(y[i])::"memory");
            STAMP(8);
            load_x4<2, 4>(xa1, xa);
            mbar_wait_fast(bars + B_XD + 8, 0);
            OUT4(2, 0, xa0, 16)
            load_x4<3, 0>(xa0, xa);
            OUT4(2, 4, xa1, 16)
            load_x4<3, 4>(xa1, xa);
            OUT4(3, 0, xa0, 16)
            OUT4(3, 4, xa1, 16)
            STAMP(9);
            return;
        }
        asm volatile("setmaxnreg.dec.sync.aligned.u32 152;");
        } else {
        if (nu) {
            cf T[8];
            ldtab_cf<2048>(T, TAB_T + t7 * 16);
            const uint32_t ep = get_epoch(bars);
            const int ka = pos_of(t7 >> 2);
            asm volatile("setp.eq.u32 p0, %0, 0;" ::"r"(__shfl_sync(~0u, t7, lane)));
            mbar_wait(bars + B_WSP, 0);
            mbar_wait(bars + B_FG, 0);
            uint32_t wd[4], wm[4], vo[32];
            const uint8_t* vp;
            int slot;
            const int kap0 = unit_of(role, 0, slot), al = 2 * kap0;
            const int kap1 = __shfl_sync(~0u, unit_of(role, 1, slot), 0);
            slot = __shfl_sync(~0u, slot, 0);
            cf be1 = twid(kap0 + 512 * q, 2048), be2 = csq(be1), be3 = cmul(be1, be2);
#pragma unroll
            for (int j = 0; j < 4; j++) {
                wd[j] = sb + OFF_WD + ((j + q) & 3) * WPITCH + (al & 15) + 2 * ka + 64 * q;
                wm[j] = sb + OFF_WM + (((role ? 3 : 4) - j - q) & 3) * WPITCH + (-al & 15) + 1024 - 2 * ka - 64 * q;
                wd[j] = __shfl_sync(~0u, wd[j], lane);
            }
#pragma unroll 1
            for (int u = 0; u < nu; u++) {
                const uint32_t buf = sb + OFF_P + u * 16384;
                float acc[64], za[32], zb[32], ya[32], yb[32], vv[64];
                const uint64_t dF = opaque(mkdesc(sb + OFF_F, 16, 1024, 1)), dB = opaque(mkdesc(buf, 4096, 512, 2));
                mbar_wait(bars + B_IN + u * 8, 0);
                if (!role) {
                    const uint32_t z = buf + w * 1024 + (fresh_lane() >> 2) * 128 + 64 + (fresh_lane() & 3) * 16;
#pragma unroll
                    for (int i = 0; i < 4; i++) sts128(z + i * 4096, 0, 0, 0, 0);
                    fence_async_sm();
                    bar_sync(3, 128);
                }
                STAMP3(22);
                wg_fence();
#pragma unroll
                for (int j = 0; j < 4; j++) mma128_ss<0, 0, 1>(acc, dF + j * 2, dB + j * 64, j);
                wg_commit();
                if (u) {
                    const uint32_t va = sb + OFF_P + (((uint32_t)(uintptr_t)vp - (uint32_t)(uintptr_t)g_X) >> 9 & 0x7c0) + ((uint32_t)(uintptr_t)vp & 31) + (fresh_lane() & 4) * 8;
                    bar_sync(3, 128);
#pragma unroll
                    for (int k = 0; k < 16; k++) sts64(va + ((k >> 1) & 1) * 8192 + (k >> 2) * 2048 + (k & 1) * 256, vo[2 * k], vo[2 * k + 1]);
                    fence_async_sm();
                    warp_arrive(bars + B_STG);
                    if (!role) { const uint32_t t = wm[0]; wm[0] = wm[1]; wm[1] = wm[2]; wm[2] = wm[3]; wm[3] = t; }
                }
                STAMP3(39);
                wg_wait<0>();
                pin(acc);
                STAMP3(30);
                uint32_t af[16], ag[16];
#pragma unroll
                for (int k = 0; k < 8; k++) {
                    uint32_t(&o)[16] = k < 4 ? af : ag;
                    const int c = k & 3;
#pragma unroll
                    for (int b = 0; b < 2; b++) {
                        const int i = 4 * (4 * ((k >> 2) * 2 + b) + c);
                        c2 x = mul2(c2{{acc[i], acc[i + 2]}, {acc[i + 1], acc[i + 3]}}, c2{T[2 * c], T[2 * c + 1]});
                        o[4 * c + b] = pk(x.a.x, x.a.y);
                        o[4 * c + 2 + b] = pk(x.b.x, x.b.y);
                    }
                    asm volatile("" : "+r"(o[4 * c]), "+r"(o[4 * c + 1]), "+r"(o[4 * c + 2]), "+r"(o[4 * c + 3])::"memory");
                    wg_fence();
                    mma64_rs<0>(k < 4 ? za : zb, o[4 * c], o[4 * c + 1], o[4 * c + 2], o[4 * c + 3], dF + c * 2, c);
                }
                wg_commit();
                STAMP3(31);
                mbar_wait_fast(bars + B_WD, u & 1);
                STAMP3(37);
                uint32_t wr[16];
#pragma unroll
                for (int i = 0; i < 16; i++) wr[i] = lds16(wd[i >> 2] + 256 * ((i >> 1) & 1) + (i & 1) * 4 * WPITCH);
                wg_wait<0>();
                pin(za);
                pin(zb);
                pinu(af);
                pinu(ag);
                STAMP3(32);
#pragma unroll
                for (int jb = 0; jb < 4; jb++) {
                    const int i = 8 * jb;
                    c2 s0 = {{za[i], za[i + 4]}, {za[i + 1], za[i + 5]}}, s2 = {{za[i + 2], za[i + 6]}, {za[i + 3], za[i + 7]}};
                    c2 s1 = {{zb[i], zb[i + 4]}, {zb[i + 1], zb[i + 5]}}, s3 = {{zb[i + 2], zb[i + 6]}, {zb[i + 3], zb[i + 7]}};
                    c2 W[4];
                    auto wcvt = [&](int j) {
                        asm volatile("shl.b32 %0, %4, 16; shl.b32 %1, %5, 16; shl.b32 %2, %6, 16; shl.b32 %3, %7, 16;"
                                     : "=&f"(W[j].a.x), "=&f"(W[j].a.y), "=&f"(W[j].b.x), "=&f"(W[j].b.y) : "r"(wr[4 * j]), "r"(wr[4 * j + 1]), "r"(wr[4 * j + 2]), "r"(wr[4 * j + 3]));
                        if ((jb & 1) == 0)
                            asm volatile("@p0 ld.shared.v2.f32 {%0,%1}, [%2];" : "+f"(W[j].a.x), "+f"(W[j].a.y) : "r"(sb + OFF_WSP + u * 64 + jb * 16 + j * 8));
                        if (jb < 3) {
#pragma unroll
                            for (int k = 4 * j; k < 4 * j + 4; k++) {
                                const int e = (k >> 1) & 1, pl = (k & 1) * 4 * WPITCH;
                                wr[k] = jb == 0 ? lds16(wd[j] + 512 + 256 * e + pl) : lds16(wm[j] - 512 * (jb - 1) - 256 * e + pl);
                            }
                        }
                        if (jb >= 2) { W[j].a.y = -W[j].a.y; W[j].b.y = -W[j].b.y; }
                    };
                    wcvt(0);
                    s2 = mul2(s2, be1);
                    s1 = fma2(s1, be2, s0);
                    wcvt(1);
                    s3 = fma2(s3, be3, s2);
                    { const c2 x = twm2(s0, s1), y = twm2(s2, s3); s0 = s1; s2 = s3; s1 = x; s3 = y; }
                    wcvt(2);
                    bfly<0>(s0, s2); bfly_mi<0>(s1, s3);
                    wcvt(3);
                    s0 = mul2(s0, W[0]); s1 = mul2(s1, W[1]);
                    bfly_tw<0>(s0, s2, W[2], s1, s3, W[3]);
                    bfly<0>(s0, s1); bfly_mi<0>(s2, s3);
                    af[4 * jb] = pk(s0.a.x, s0.b.x); af[4 * jb + 1] = pk(s3.a.x, s3.b.x); af[4 * jb + 2] = pk(s0.a.y, s0.b.y); af[4 * jb + 3] = pk(s3.a.y, s3.b.y);
                    ag[4 * jb] = pk(s1.a.x, s1.b.x); ag[4 * jb + 1] = pk(s2.a.x, s2.b.x); ag[4 * jb + 2] = pk(s1.a.y, s1.b.y); ag[4 * jb + 3] = pk(s2.a.y, s2.b.y);
                }
                pinu(af);
                pinu(ag);
                warp_arrive(bars + B_WFREE);
                wg_fence();
#pragma unroll
                for (int j = 0; j < 4; j++) mma64_rs<1>(ya, af[4 * j], af[4 * j + 1], af[4 * j + 2], af[4 * j + 3], dF + j * 128, j);
                wg_commit();
#pragma unroll
                for (int j = 0; j < 4; j++) mma64_rs<1>(yb, ag[4 * j], ag[4 * j + 1], ag[4 * j + 2], ag[4 * j + 3], dF + j * 128, j);
                wg_commit();
                STAMP3(33);
                {
                    const uint32_t a0 = buf + (mi & 1) * 4096 + (16 * w + 8 * (mi >> 1) + gl) * 64 + ((gl >> 1) << 4);
#pragma unroll
                    for (int h = 0; h < 2; h++) {
                        if (h == 0) { wg_wait<1>(); pin(ya); pinu(af); STAMP3(34); } else { wg_wait<0>(); pin(yb); pinu(ag); }
                        const float(&yy)[32] = h ? yb : ya;
#pragma unroll
                        for (int c = 0; c < 4; c++) {
                            const int i = 8 * ((c + 2 * h) & 3), k = 8 * ((c + 2 * h + 1) & 3) + 2;
                            c2 x = {cmulc({yy[i], yy[i + 1]}, T[2 * c]), cmulc({yy[k], yy[k + 1]}, T[2 * c])};
                            fin<1>(x);
                            c2 y = {cmulc({yy[i + 4], yy[i + 5]}, T[2 * c + 1]), cmulc({yy[k + 4], yy[k + 5]}, T[2 * c + 1])};
                            fin<1>(y);
                            stsm4((a0 ^ (c << 4)) + h * 8192, pk(x.a.x, y.a.x), pk(x.b.x, y.b.x), pk(x.a.y, y.a.y), pk(x.b.y, y.b.y));
                        }
                    }
                }
                STAMP3(38);
                fence_async_sm();
                bar_sync(3, 128);
                wg_fence();
#pragma unroll
                for (int j = 0; j < 4; j++) mma128_ss<0, 1, 1>(vv, dF + j * 128, dB + j * 64, j);
                wg_commit();
                STAMP3(35);
                const int lane = fresh_lane(), g = lane >> 2, q = lane & 3;
                vp = padd(g_X + (4 << 20) + w * (8 * 32768) + (role ? u : 1) * 16384 + slot * 64,
                                         (g >> 1) * 32768 + (role ? g & 1 : u) * 32 + (((q ^ (slot >> 1)) & 1) << 4) + (q >> 1) * 8);
                const uint32_t tmask = (((g & 1) == ((slot >> 3) & 1) || !role) && q == ((slot >> 1) & 2)) ? ~1u : ~0u, tbit = (ep ^ (role + u ? 0 : g)) & ~tmask;
                be1 = twid(kap1 + 512 * q, 2048); be2 = csq(be1); be3 = cmul(be1, be2);
                asm volatile("pmevent 1;" : "+f"(be1.x), "+f"(be1.y), "+f"(be2.x), "+f"(be2.y), "+f"(be3.x), "+f"(be3.y), "+l"(vp)::"memory");
                wg_wait<0>();
                pin(vv);
                STAMP3(36);
#pragma unroll
                for (int k = 0; k < 16; k++) {
                    const int i = 8 * (k >> 1) + 2 * (k & 1);
                    vo[2 * k] = (pk(vv[i], vv[i + 1]) & tmask) | tbit;
                    vo[2 * k + 1] = pk(vv[i + 4], vv[i + 5]);
                }
                pinu(vo);
            }
            if (!role) mbar_wait(bars + B_IN + 16, 0);
            warp_arrive(bars + B_STG);
            const bool odd = fresh_lane() & 4;
            store_v<0, 4>(vo, vp, role || !odd);
            asm volatile("@p0 red.relaxed.gpu.global.add.u32 [%0], 1;" ::"l"(g_cnt + 32 + nu * 32) : "memory");
            store_v<4, 16>(vo, vp, role || odd);
            if (!spare) bar_arrive(9, 256);
        }
        if (spare) return;
        }
        {
            constexpr int Y = YP3;
            uint32_t sp[8];
            cf tw[8];
            ldtab<2, 2048>(sp, TAB_SP + fb * 4096 + t7 * 16);
            ldtab_cf<16>(tw, TAB_TW3 + fb * 2048 + (t7 >> 2) * 64);
            const uint64_t dF = opaque(mkdesc(sb + OFF_F, 16, 1024, 1)), dB = opaque(mkdesc(sb + OFF_P + hf * 8192, 1024, 256, 3));
            const uint8_t* op = padd(p.out + (1024 + fb) * 2048 + fcb * 32 + hf * 16, (t7 >> 2) * 32768 + (q >> 1) * 16 + (q & 1) * 32);
            float acc[64], out[64];
            mbar_wait(bars + B_IN + 24, 0);
            mbar_wait(bars + B_FG, 1);
            STAMP(25);
            pinu(sp);
            wg_fence();
#pragma unroll
            for (int j = 0; j < 4; j++) {
                const uint64_t db = dB + (j >> 1) * 1024 + (j & 1) * 32;
                mma112_ss(acc, dF + j * 2, db + 64, j);
                if (j & 1) mma16_rs(acc, 0u, sp[2 * j], 0u, sp[2 * j + 1], db, 1);
                else mma16_rs(acc, sp[2 * j], 0u, sp[2 * j + 1], 0u, db, j);
            }
            wg_commit();
            wg_wait<0>();
            pin(acc);
            pinu(sp);
            warp_arrive(bars + B_P3M);
            if (!hf) bar_sync(5, 256);
#pragma unroll
            for (int cl = 0; cl < 2; cl++) {
                c2 z[8];
#pragma unroll
                for (int n = 0; n < 8; n++) {
                    const int i = 4 * (2 * n + cl);
                    z[n] = {{acc[i], acc[i + 2]}, {acc[i + 1], acc[i + 3]}};
                }
                z[0] = {{z[0].a.x + z[0].a.y, z[0].a.x - z[0].a.y}, {z[0].b.x + z[0].b.y, z[0].b.x - z[0].b.y}};
                z[4] = mul2(z[4], tw[4]);
                fin<Y>(z[0], z[4]);
#pragma unroll
                for (int n = 1; n < 4; n++) {
                    const cf iw = n == 1 ? cf{0.38268343236508977f, 0.92387953251128674f}
                                         : (n == 2 ? cf{0.70710678118654752f, 0.70710678118654752f} : cf{0.92387953251128674f, 0.38268343236508977f});
                    c2 y = mul2(z[n], tw[n]);
                    fin<Y>(y);
                    const cf t = {tw[8 - n].x, -tw[8 - n].y};
                    c2 E = fma2(c2{{z[8 - n].a.x, -z[8 - n].a.y}, {z[8 - n].b.x, -z[8 - n].b.y}}, t, y);
                    fin<Y>(E);
                    z[n] = fma2(twm2(y, E), iw, E);
                    fin<Y>(z[n]);
                    z[8 - n] = {{fmaf(2.f, E.a.x, -z[n].a.x), fmaf(-2.f, E.a.y, z[n].a.y)}, {fmaf(2.f, E.b.x, -z[n].b.x), fmaf(-2.f, E.b.y, z[n].b.y)}};
                }
                dft8<false, Y>(z, tw);
#pragma unroll
                for (int m = 0; m < 8; m++) {
                    out[8 * m + 2 * cl] = z[m].a.x; out[8 * m + 2 * cl + 1] = z[m].b.x;
                    out[8 * m + 4 + 2 * cl] = z[m].a.y; out[8 * m + 5 + 2 * cl] = z[m].b.y;
                }
            }
            pin(out);
            if (hf) bar_arrive(5, 256);
            if (hf) STAMP(26);
#pragma unroll
            for (int m = 0; m < 16; m++) {
                asm volatile("st.global.v4.f32 [%0], {%1,%2,%3,%4};" ::"l"(op + (m - 8) * (1 << 20)), "f"(out[4 * m]), "f"(out[4 * m + 1]), "f"(out[4 * m + 2]), "f"(out[4 * m + 3]) : "memory");
                if (PACE_O && m < 15 && m % PACE_ON == PACE_ON - 1)
                    asm volatile("{.reg .pred p; mbarrier.test_wait.parity.shared::cta.b64 p, [%0], 0; @!p nanosleep.u32 %1;}" ::"r"(bars + B_DONE), "n"(PACE_O) : "memory");
            }
            STAMP(27);
        }
    }
}

typedef CUresult (*EncodeFn)(CUtensorMap*, CUtensorMapDataType, cuuint32_t, void*, const cuuint64_t*, const cuuint64_t*, const cuuint32_t*,
                             const cuuint32_t*, CUtensorMapInterleave, CUtensorMapSwizzle, CUtensorMapL2promotion, CUtensorMapFloatOOBfill);

static CUtensorMap make_map(EncodeFn enc, const void* ptr, int rank, const cuuint64_t* dims, const cuuint64_t* strides, const cuuint32_t* box,
                            CUtensorMapSwizzle swz, CUtensorMapL2promotion promo, CUtensorMapDataType dt = CU_TENSOR_MAP_DATA_TYPE_BFLOAT16) {
    CUtensorMap m;
    const cuuint32_t es[5] = {1, 1, 1, 1, 1};
    enc(&m, dt, rank, const_cast<void*>(ptr), dims, strides, box, es, CU_TENSOR_MAP_INTERLEAVE_NONE, swz, promo,
        CU_TENSOR_MAP_FLOAT_OOB_FILL_NONE);
    return m;
}

extern "C" void kernel_launch(void* const* d_in, const int* in_sizes, int n_in, void* d_out, int out_size) {
    void* fn = nullptr;
    cudaDriverEntryPointQueryResult qr;
    cudaGetDriverEntryPoint("cuTensorMapEncodeTiled", &fn, cudaEnableDefault, &qr);
    EncodeFn enc = (EncodeFn)fn;
    void* pX;
    cudaGetSymbolAddress(&pX, g_X);
    const CUtensorMapL2promotion P256 = CU_TENSOR_MAP_L2_PROMOTION_L2_256B, P0 = CU_TENSOR_MAP_L2_PROMOTION_NONE;

    const cuuint64_t dX[5] = {1024, 2, 4, 16, 16}, sX[4] = {2048, 32 * 2048, 2 * 2048, 128 * 2048};
    const cuuint32_t bX[5] = {64, 2, 4, 16, 1};
    CUtensorMap tmX = make_map(enc, d_in[3], 5, dX, sX, bX, CU_TENSOR_MAP_SWIZZLE_128B, P256);
    const cuuint64_t dXd[4] = {64, 2048, 2, 16}, sXd[3] = {2048, 64 * 2048, 128};
    const cuuint32_t bXd[4] = {64, 16, 2, 2};
    CUtensorMap tmXd = make_map(enc, d_in[3], 4, dXd, sXd, bXd, CU_TENSOR_MAP_SWIZZLE_128B, P256);
    const cuuint64_t dB[4] = {1024, 8, 4, 32}, sB[3] = {2048, 256 * 2048, 8 * 2048};
    const cuuint32_t bB4[4] = {64, 8, 2, 4};
    CUtensorMap tmBre = make_map(enc, d_in[6], 4, dB, sB, bB4, CU_TENSOR_MAP_SWIZZLE_128B, P256);
    CUtensorMap tmBim = make_map(enc, d_in[7], 4, dB, sB, bB4, CU_TENSOR_MAP_SWIZZLE_128B, P256);
    const cuuint64_t dC[5] = {1024, 2, 4, 2, 64}, sC[4] = {2048, 4 * 2048, 2 * 2048, 16 * 2048};
    const cuuint32_t bC[5] = {64, 2, 4, 2, 4};
    CUtensorMap tmCre = make_map(enc, d_in[8], 5, dC, sC, bC, CU_TENSOR_MAP_SWIZZLE_128B, P256);
    CUtensorMap tmCim = make_map(enc, d_in[9], 5, dC, sC, bC, CU_TENSOR_MAP_SWIZZLE_128B, P256);

    const cuuint64_t dU[2] = {8192, 256}, sU[1] = {16384};
    const cuuint32_t bU[2] = {64, 64};
    CUtensorMap tmUst = make_map(enc, pX, 2, dU, sU, bU, CU_TENSOR_MAP_SWIZZLE_128B, P0);
    const cuuint64_t dV[2] = {16384, 128}, sV[1] = {32768};
    const cuuint32_t bV[2] = {32, 128};
    CUtensorMap tmVst = make_map(enc, (uint8_t*)pX + (4 << 20), 2, dV, sV, bV, CU_TENSOR_MAP_SWIZZLE_NONE, P0);
    const cuuint64_t dF[2] = {512 * 1026 / 8, 4}, sF[1] = {512 * 1026};
    const cuuint32_t bF[2] = {WPITCH / 8, 4};
    CUtensorMap tmWr = make_map(enc, d_in[1], 2, dF, sF, bF, CU_TENSOR_MAP_SWIZZLE_NONE, P0, CU_TENSOR_MAP_DATA_TYPE_UINT64);
    CUtensorMap tmWi = make_map(enc, d_in[2], 2, dF, sF, bF, CU_TENSOR_MAP_SWIZZLE_NONE, P0, CU_TENSOR_MAP_DATA_TYPE_UINT64);

    const cuuint64_t dA[3] = {1024, 64, 32}, sA[2] = {32 * 2048, 2048};
    const cuuint32_t bA[3] = {32, 64, 1};
    CUtensorMap tmXa = make_map(enc, d_in[0], 3, dA, sA, bA, CU_TENSOR_MAP_SWIZZLE_64B, CU_TENSOR_MAP_L2_PROMOTION_L2_128B);

    Params p;
    p.wr = (const __nv_bfloat16*)d_in[1];
    p.wi = (const __nv_bfloat16*)d_in[2];
    p.lre = (const __nv_bfloat16*)d_in[4];
    p.lim = (const __nv_bfloat16*)d_in[5];
    p.ldt = (const __nv_bfloat16*)d_in[10];
    p.dsk = (const __nv_bfloat16*)d_in[11];
    p.out = (float*)d_out;
    int dev = 0, sms = 0;
    cudaGetDevice(&dev);
    cudaDeviceGetAttribute(&sms, cudaDevAttrMultiProcessorCount, dev);
    auto kernel = sms == 132 ? fused_kernel<true> : fused_kernel<false>;
    cudaFuncSetAttribute(kernel, cudaFuncAttributeMaxDynamicSharedMemorySize, SMEM_BYTES);
    kernel<<<132, 512, SMEM_BYTES>>>(tmX, tmBre, tmBim, tmCre, tmCim, tmXd, tmUst, tmVst, tmWr, tmWi, tmXa, p);
}
```

```cpp
#include <cuda_runtime.h>
#include <cuda.h>
#include <cuda_bf16.h>
#include <stdint.h>

#define NST 5
#define WPITCH 1056
#define OFF_P (NST * 32768)
#define OFF_F (OFF_P + 32768)
#define OFF_WD (OFF_F + 8192)
#define OFF_WM (OFF_WD + 8 * WPITCH)
#define OFF_BAR (OFF_F + 32768)
#define OFF_LAM (OFF_BAR + 432)
#define OFF_WSP (OFF_LAM + 2048)
#define OFF_PROF (OFF_WSP + 128)
#define SMEM_BYTES OFF_PROF
#define B_FULL 0
#define B_HL 40
#define B_EP 120
#define B_HR 128
#define B_XD 144
#define B_FG 160
#define B_WSP 168
#define B_WD 176
#define B_DONE 184
#define B_LD 192
#define B_RAW 200
#define B_LAM 208
#define B_IN 216
#define B_XIN 248
#define B_EMPTY 256
#define B_STG 320
#define B_WFREE 328
#define B_HOWN 336
#define B_STGU 368
#define B_P3M 384
#define B_EPOCH 416

#define XA_PACE 200
#define PACE_O 200
#define PACE_ON 2
#define TAB_T0 500
#define LAM_T0 2000
#define XA_N0 2
#define PACE_X 200
#define SKEW 4
#define SPIN_LIMIT (1u << 15)

__device__ __align__(1024) uint8_t g_X[8 << 20];
__device__ __align__(1024) uint8_t g_H[8 << 20];
__device__ __align__(1024) uint4 g_carry[16 * 512];
__device__ __align__(128) unsigned g_cnt[128];
__device__ __align__(128) unsigned g_epoch[132 * 8];

#define STAMP(i) do { } while (0)
#define STAMPO(i, o) do { } while (0)
#define STAMPW(a, b) do { } while (0)
#define STAMPX(a, b) do { } while (0)
#define STAMP5(i) do { } while (0)
#define STAMP3(i) do { } while (0)

#define TAB_FG 0
#define TAB_G 8192
#define TAB_F1 40960
#define TAB_T 49152
#define TAB_SP 57344
#define TAB_TW1 73728
#define TAB_TW3 75776
#define TAB_PC 83968
__device__ __align__(1024) const uint32_t g_tab[21248] = {
0x80003d80,0x80003d80,0x80003d80,0x80003d80,0x80003d80,0x80003d80,0x80003d80,0x80003d80,0x80003d80,0x80003d80,0x80003d80,0x80003d80,0x80003d80,0x80003d80,0x80003d80,0x80003d80,
0x80003d80,0x80003d80,0x80003d80,0x80003d80,0x80003d80,0x80003d80,0x80003d80,0x80003d80,0x80003d80,0x80003d80,0x80003d80,0x80003d80,0x80003d80,0x80003d80,0x80003d80,0x80003d80,
0x3d353d35,0x3d35bd35,0xbd35bd35,0xbd353d35,0x80003d80,0x3d800000,0x8000bd80,0xbd800000,0x3d353d35,0x3d35bd35,0xbd35bd35,0xbd353d35,0x80003d80,0x3d800000,0x8000bd80,0xbd800000,
0x3d353d35,0x3d35bd35,0xbd35bd35,0xbd353d35,0x80003d80,0x3d800000,0x8000bd80,0xbd800000,0x3d353d35,0x3d35bd35,0xbd35bd35,0xbd353d35,0x80003d80,0x3d800000,0x8000bd80,0xbd800000,
0x3d800000,0x3d6dbcc4,0x3d35bd35,0x3cc4bd6d,0x3d7bbc48,0x3d55bd0e,0x3d0ebd55,0x3c48bd7b,0x80003d80,0x3cc43d6d,0x3d353d35,0x3d6d3cc4,0x3c483d7b,0x3d0e3d55,0x3d553d0e,0x3d7b3c48,
0xbd800000,0xbd6d3cc4,0xbd353d35,0xbcc43d6d,0xbd7b3c48,0xbd553d0e,0xbd0e3d55,0xbc483d7b,0x8000bd80,0xbcc4bd6d,0xbd35bd35,0xbd6dbcc4,0xbc48bd7b,0xbd0ebd55,0xbd55bd0e,0xbd7bbc48,
0x3d0ebd55,0xbd7bbc48,0x3c483d7b,0x3d55bd0e,0x3d800000,0xbcc4bd6d,0xbd353d35,0x3d6d3cc4,0x3d553d0e,0x3c48bd7b,0xbd7b3c48,0x3d0e3d55,0x80003d80,0x3d6dbcc4,0xbd35bd35,0xbcc43d6d,
0xbd0e3d55,0x3d7b3c48,0xbc48bd7b,0xbd553d0e,0xbd800000,0x3cc43d6d,0x3d35bd35,0xbd6dbcc4,0xbd55bd0e,0xbc483d7b,0x3d7bbc48,0xbd0ebd55,0x8000bd80,0xbd6d3cc4,0x3d353d35,0x3cc4bd6d,
0x80003d80,0x3d353d35,0x3d800000,0x3d35bd35,0x3cc43d6d,0x3d6d3cc4,0x3d6dbcc4,0x3cc4bd6d,0x8000bd80,0xbd35bd35,0xbd800000,0xbd353d35,0xbcc4bd6d,0xbd6dbcc4,0xbd6d3cc4,0xbcc43d6d,
0x80003d80,0x3d353d35,0x3d800000,0x3d35bd35,0x3cc43d6d,0x3d6d3cc4,0x3d6dbcc4,0x3cc4bd6d,0x8000bd80,0xbd35bd35,0xbd800000,0xbd353d35,0xbcc4bd6d,0xbd6dbcc4,0xbd6d3cc4,0xbcc43d6d,
0x3d6d3cc4,0xbcc4bd6d,0xbcc43d6d,0x3d6dbcc4,0x80003d80,0x3d35bd35,0xbd800000,0x3d353d35,0xbd6dbcc4,0x3cc43d6d,0x3cc4bd6d,0xbd6d3cc4,0x8000bd80,0xbd353d35,0x3d800000,0xbd35bd35,
0x3d6d3cc4,0xbcc4bd6d,0xbcc43d6d,0x3d6dbcc4,0x80003d80,0x3d35bd35,0xbd800000,0x3d353d35,0xbd6dbcc4,0x3cc43d6d,0x3cc4bd6d,0xbd6d3cc4,0x8000bd80,0xbd353d35,0x3d800000,0xbd35bd35,
0x3d800000,0x3cc4bd6d,0xbd35bd35,0xbd6d3cc4,0x3d55bd0e,0xbc48bd7b,0xbd7bbc48,0xbd0e3d55,0x8000bd80,0xbd6dbcc4,0xbd353d35,0x3cc43d6d,0xbd0ebd55,0xbd7b3c48,0xbc483d7b,0x3d553d0e,
0xbd800000,0xbcc43d6d,0x3d353d35,0x3d6dbcc4,0xbd553d0e,0x3c483d7b,0x3d7b3c48,0x3d0ebd55,0x80003d80,0x3d6d3cc4,0x3d35bd35,0xbcc4bd6d,0x3d0e3d55,0x3d7bbc48,0x3c48bd7b,0xbd55bd0e,
0x3c48bd7b,0xbd0e3d55,0x3d55bd0e,0xbd7b3c48,0x3d800000,0xbd6dbcc4,0x3d353d35,0xbcc4bd6d,0xbd7bbc48,0x3d553d0e,0xbd0ebd55,0x3c483d7b,0x8000bd80,0xbcc43d6d,0x3d35bd35,0xbd6d3cc4,
0xbc483d7b,0x3d0ebd55,0xbd553d0e,0x3d7bbc48,0xbd800000,0x3d6d3cc4,0xbd35bd35,0x3cc43d6d,0x3d7b3c48,0xbd55bd0e,0x3d0e3d55,0xbc48bd7b,0x80003d80,0x3cc4bd6d,0xbd353d35,0x3d6dbcc4,
0x3d800000,0x3d800000,0x3d800000,0x3d800000,0x3d800000,0x3d800000,0x3d800000,0x3d800000,0x3d800000,0x3d800000,0x3d800000,0x3d800000,0x3d800000,0x3d800000,0x3d800000,0x3d800000,
0x3d800000,0x3d800000,0x3d800000,0x3d800000,0x3d800000,0x3d800000,0x3d800000,0x3d800000,0x3d800000,0x3d800000,0x3d800000,0x3d800000,0x3d800000,0x3d800000,0x3d800000,0x3d800000,
0x3d35bd35,0xbd35bd35,0xbd353d35,0x3d353d35,0x3d800000,0xbd80,0xbd800000,0x3d80,0x3d35bd35,0xbd35bd35,0xbd353d35,0x3d353d35,0x3d800000,0xbd80,0xbd800000,0x3d80,
0x3d35bd35,0xbd35bd35,0xbd353d35,0x3d353d35,0x3d800000,0xbd80,0xbd800000,0x3d80,0x3d35bd35,0xbd35bd35,0xbd353d35,0x3d353d35,0x3d800000,0xbd80,0xbd800000,0x3d80,
0xbd80,0xbcc4bd6d,0xbd35bd35,0xbd6dbcc4,0xbc48bd7b,0xbd0ebd55,0xbd55bd0e,0xbd7bbc48,0x3d800000,0x3d6dbcc4,0x3d35bd35,0x3cc4bd6d,0x3d7bbc48,0x3d55bd0e,0x3d0ebd55,0x3c48bd7b,
0x3d80,0x3cc43d6d,0x3d353d35,0x3d6d3cc4,0x3c483d7b,0x3d0e3d55,0x3d553d0e,0x3d7b3c48,0xbd800000,0xbd6d3cc4,0xbd353d35,0xbcc43d6d,0xbd7b3c48,0xbd553d0e,0xbd0e3d55,0xbc483d7b,
0xbd55bd0e,0xbc483d7b,0x3d7bbc48,0xbd0ebd55,0xbd80,0xbd6d3cc4,0x3d353d35,0x3cc4bd6d,0x3d0ebd55,0xbd7bbc48,0x3c483d7b,0x3d55bd0e,0x3d800000,0xbcc4bd6d,0xbd353d35,0x3d6d3cc4,
0x3d553d0e,0x3c48bd7b,0xbd7b3c48,0x3d0e3d55,0x3d80,0x3d6dbcc4,0xbd35bd35,0xbcc43d6d,0xbd0e3d55,0x3d7b3c48,0xbc48bd7b,0xbd553d0e,0xbd800000,0x3cc43d6d,0x3d35bd35,0xbd6dbcc4,
0x3d800000,0x3d35bd35,0xbd80,0xbd35bd35,0x3d6dbcc4,0x3cc4bd6d,0xbcc4bd6d,0xbd6dbcc4,0xbd800000,0xbd353d35,0x3d80,0x3d353d35,0xbd6d3cc4,0xbcc43d6d,0x3cc43d6d,0x3d6d3cc4,
0x3d800000,0x3d35bd35,0xbd80,0xbd35bd35,0x3d6dbcc4,0x3cc4bd6d,0xbcc4bd6d,0xbd6dbcc4,0xbd800000,0xbd353d35,0x3d80,0x3d353d35,0xbd6d3cc4,0xbcc43d6d,0x3cc43d6d,0x3d6d3cc4,
0x3cc4bd6d,0xbd6d3cc4,0x3d6d3cc4,0xbcc4bd6d,0x3d800000,0xbd35bd35,0x3d80,0x3d35bd35,0xbcc43d6d,0x3d6dbcc4,0xbd6dbcc4,0x3cc43d6d,0xbd800000,0x3d353d35,0xbd80,0xbd353d35,
0x3cc4bd6d,0xbd6d3cc4,0x3d6d3cc4,0xbcc4bd6d,0x3d800000,0xbd35bd35,0x3d80,0x3d35bd35,0xbcc43d6d,0x3d6dbcc4,0xbd6dbcc4,0x3cc43d6d,0xbd800000,0x3d353d35,0xbd80,0xbd353d35,
0xbd80,0xbd6dbcc4,0xbd353d35,0x3cc43d6d,0xbd0ebd55,0xbd7b3c48,0xbc483d7b,0x3d553d0e,0xbd800000,0xbcc43d6d,0x3d353d35,0x3d6dbcc4,0xbd553d0e,0x3c483d7b,0x3d7b3c48,0x3d0ebd55,
0x3d80,0x3d6d3cc4,0x3d35bd35,0xbcc4bd6d,0x3d0e3d55,0x3d7bbc48,0x3c48bd7b,0xbd55bd0e,0x3d800000,0x3cc4bd6d,0xbd35bd35,0xbd6d3cc4,0x3d55bd0e,0xbc48bd7b,0xbd7bbc48,0xbd0e3d55,
0xbd7bbc48,0x3d553d0e,0xbd0ebd55,0x3c483d7b,0xbd80,0xbcc43d6d,0x3d35bd35,0xbd6d3cc4,0xbc483d7b,0x3d0ebd55,0xbd553d0e,0x3d7bbc48,0xbd800000,0x3d6d3cc4,0xbd35bd35,0x3cc43d6d,
0x3d7b3c48,0xbd55bd0e,0x3d0e3d55,0xbc48bd7b,0x3d80,0x3cc4bd6d,0xbd353d35,0x3d6dbcc4,0x3c48bd7b,0xbd0e3d55,0x3d55bd0e,0xbd7b3c48,0x3d800000,0xbd6dbcc4,0x3d353d35,0xbcc4bd6d,
0x80003d80,0x8000bd80,0x80003d80,0x8000bd80,0x3d800000,0xbd800000,0x3d800000,0xbd800000,0x80003d80,0x8000bd80,0x80003d80,0x8000bd80,0x3d800000,0xbd800000,0x3d800000,0xbd800000,
0x80003d80,0x8000bd80,0x80003d80,0x8000bd80,0x3d800000,0xbd800000,0x3d800000,0xbd800000,0x80003d80,0x8000bd80,0x80003d80,0x8000bd80,0x3d800000,0xbd800000,0x3d800000,0xbd800000,
0x3d35bd35,0x3d353d35,0xbd353d35,0xbd35bd35,0x80003d80,0xbd800000,0x8000bd80,0x3d800000,0x3d35bd35,0x3d353d35,0xbd353d35,0xbd35bd35,0x80003d80,0xbd800000,0x8000bd80,0x3d800000,
0x3d35bd35,0x3d353d35,0xbd353d35,0xbd35bd35,0x80003d80,0xbd800000,0x8000bd80,0x3d800000,0x3d35bd35,0x3d353d35,0xbd353d35,0xbd35bd35,0x80003d80,0xbd800000,0x8000bd80,0x3d800000,
0x3d800000,0xbd6d3cc4,0x3d35bd35,0xbcc43d6d,0xbc48bd7b,0x3d0e3d55,0xbd55bd0e,0x3d7b3c48,0x80003d80,0xbcc4bd6d,0x3d353d35,0xbd6dbcc4,0x3d7bbc48,0xbd553d0e,0x3d0ebd55,0xbc483d7b,
0xbd800000,0x3d6dbcc4,0xbd353d35,0x3cc4bd6d,0x3c483d7b,0xbd0ebd55,0x3d553d0e,0xbd7bbc48,0x8000bd80,0x3cc43d6d,0xbd35bd35,0x3d6d3cc4,0xbd7b3c48,0x3d55bd0e,0xbd0e3d55,0x3c48bd7b,
0xbd55bd0e,0x3c48bd7b,0x3d7bbc48,0x3d0e3d55,0x3d800000,0x3cc43d6d,0xbd353d35,0xbd6dbcc4,0x3d0ebd55,0x3d7b3c48,0x3c483d7b,0xbd553d0e,0x80003d80,0xbd6d3cc4,0xbd35bd35,0x3cc4bd6d,
0x3d553d0e,0xbc483d7b,0xbd7b3c48,0xbd0ebd55,0xbd800000,0xbcc4bd6d,0x3d35bd35,0x3d6d3cc4,0xbd0e3d55,0xbd7bbc48,0xbc48bd7b,0x3d55bd0e,0x8000bd80,0x3d6dbcc4,0x3d353d35,0xbcc43d6d,
0x80003d80,0xbd35bd35,0x3d800000,0xbd353d35,0x3d6dbcc4,0xbcc43d6d,0xbcc4bd6d,0x3d6d3cc4,0x8000bd80,0x3d353d35,0xbd800000,0x3d35bd35,0xbd6d3cc4,0x3cc4bd6d,0x3cc43d6d,0xbd6dbcc4,
0x80003d80,0xbd35bd35,0x3d800000,0xbd353d35,0x3d6dbcc4,0xbcc43d6d,0xbcc4bd6d,0x3d6d3cc4,0x8000bd80,0x3d353d35,0xbd800000,0x3d35bd35,0xbd6d3cc4,0x3cc4bd6d,0x3cc43d6d,0xbd6dbcc4,
0x3cc4bd6d,0x3d6dbcc4,0x3d6d3cc4,0x3cc43d6d,0x80003d80,0xbd353d35,0xbd800000,0xbd35bd35,0xbcc43d6d,0xbd6d3cc4,0xbd6dbcc4,0xbcc4bd6d,0x8000bd80,0x3d35bd35,0x3d800000,0x3d353d35,
0x3cc4bd6d,0x3d6dbcc4,0x3d6d3cc4,0x3cc43d6d,0x80003d80,0xbd353d35,0xbd800000,0xbd35bd35,0xbcc43d6d,0xbd6d3cc4,0xbd6dbcc4,0xbcc4bd6d,0x8000bd80,0x3d35bd35,0x3d800000,0x3d353d35,
0x3d800000,0xbcc43d6d,0xbd35bd35,0x3d6dbcc4,0xbd0ebd55,0x3d7bbc48,0xbc483d7b,0xbd55bd0e,0x8000bd80,0x3d6d3cc4,0xbd353d35,0xbcc4bd6d,0xbd553d0e,0xbc48bd7b,0x3d7b3c48,0xbd0e3d55,
0xbd800000,0x3cc4bd6d,0x3d353d35,0xbd6d3cc4,0x3d0e3d55,0xbd7b3c48,0x3c48bd7b,0x3d553d0e,0x80003d80,0xbd6dbcc4,0x3d35bd35,0x3cc43d6d,0x3d55bd0e,0x3c483d7b,0xbd7bbc48,0x3d0ebd55,
0xbd7bbc48,0xbd55bd0e,0xbd0ebd55,0xbc48bd7b,0x3d800000,0x3d6d3cc4,0x3d353d35,0x3cc43d6d,0xbc483d7b,0xbd0e3d55,0xbd553d0e,0xbd7b3c48,0x8000bd80,0x3cc4bd6d,0x3d35bd35,0x3d6dbcc4,
0x3d7b3c48,0x3d553d0e,0x3d0e3d55,0x3c483d7b,0xbd800000,0xbd6dbcc4,0xbd35bd35,0xbcc4bd6d,0x3c48bd7b,0x3d0ebd55,0x3d55bd0e,0x3d7bbc48,0x80003d80,0xbcc43d6d,0xbd353d35,0xbd6d3cc4,
0x3d800000,0xbd800000,0x3d800000,0xbd800000,0xbd80,0x3d80,0xbd80,0x3d80,0x3d800000,0xbd800000,0x3d800000,0xbd800000,0xbd80,0x3d80,0xbd80,0x3d80,
0x3d800000,0xbd800000,0x3d800000,0xbd800000,0xbd80,0x3d80,0xbd80,0x3d80,0x3d800000,0xbd800000,0x3d800000,0xbd800000,0xbd80,0x3d80,0xbd80,0x3d80,
0xbd35bd35,0x3d35bd35,0x3d353d35,0xbd353d35,0x3d800000,0x3d80,0xbd800000,0xbd80,0xbd35bd35,0x3d35bd35,0x3d353d35,0xbd353d35,0x3d800000,0x3d80,0xbd800000,0xbd80,
0xbd35bd35,0x3d35bd35,0x3d353d35,0xbd353d35,0x3d800000,0x3d80,0xbd800000,0xbd80,0xbd35bd35,0x3d35bd35,0x3d353d35,0xbd353d35,0x3d800000,0x3d80,0xbd800000,0xbd80,
0xbd80,0x3cc43d6d,0xbd35bd35,0x3d6d3cc4,0xbd7b3c48,0x3d55bd0e,0xbd0e3d55,0x3c48bd7b,0x3d800000,0xbd6d3cc4,0x3d35bd35,0xbcc43d6d,0xbc48bd7b,0x3d0e3d55,0xbd55bd0e,0x3d7b3c48,
0x3d80,0xbcc4bd6d,0x3d353d35,0xbd6dbcc4,0x3d7bbc48,0xbd553d0e,0x3d0ebd55,0xbc483d7b,0xbd800000,0x3d6dbcc4,0xbd353d35,0x3cc4bd6d,0x3c483d7b,0xbd0ebd55,0x3d553d0e,0xbd7bbc48,
0xbd0e3d55,0xbd7bbc48,0xbc48bd7b,0x3d55bd0e,0xbd80,0x3d6dbcc4,0x3d353d35,0xbcc43d6d,0xbd55bd0e,0x3c48bd7b,0x3d7bbc48,0x3d0e3d55,0x3d800000,0x3cc43d6d,0xbd353d35,0xbd6dbcc4,
0x3d0ebd55,0x3d7b3c48,0x3c483d7b,0xbd553d0e,0x3d80,0xbd6d3cc4,0xbd35bd35,0x3cc4bd6d,0x3d553d0e,0xbc483d7b,0xbd7b3c48,0xbd0ebd55,0xbd800000,0xbcc4bd6d,0x3d35bd35,0x3d6d3cc4,
0x3d800000,0xbd353d35,0xbd80,0x3d353d35,0xbcc4bd6d,0x3d6d3cc4,0xbd6d3cc4,0x3cc4bd6d,0xbd800000,0x3d35bd35,0x3d80,0xbd35bd35,0x3cc43d6d,0xbd6dbcc4,0x3d6dbcc4,0xbcc43d6d,
0x3d800000,0xbd353d35,0xbd80,0x3d353d35,0xbcc4bd6d,0x3d6d3cc4,0xbd6d3cc4,0x3cc4bd6d,0xbd800000,0x3d35bd35,0x3d80,0xbd35bd35,0x3cc43d6d,0xbd6dbcc4,0x3d6dbcc4,0xbcc43d6d,
0xbd6dbcc4,0xbcc4bd6d,0x3cc4bd6d,0x3d6dbcc4,0x3d800000,0x3d353d35,0x3d80,0xbd353d35,0x3d6d3cc4,0x3cc43d6d,0xbcc43d6d,0xbd6d3cc4,0xbd800000,0xbd35bd35,0xbd80,0x3d35bd35,
0xbd6dbcc4,0xbcc4bd6d,0x3cc4bd6d,0x3d6dbcc4,0x3d800000,0x3d353d35,0x3d80,0xbd353d35,0x3d6d3cc4,0x3cc43d6d,0xbcc43d6d,0xbd6d3cc4,0xbd800000,0xbd35bd35,0xbd80,0x3d35bd35,
0xbd80,0x3d6d3cc4,0xbd353d35,0xbcc4bd6d,0xbd553d0e,0xbc48bd7b,0x3d7b3c48,0xbd0e3d55,0xbd800000,0x3cc4bd6d,0x3d353d35,0xbd6d3cc4,0x3d0e3d55,0xbd7b3c48,0x3c48bd7b,0x3d553d0e,
0x3d80,0xbd6dbcc4,0x3d35bd35,0x3cc43d6d,0x3d55bd0e,0x3c483d7b,0xbd7bbc48,0x3d0ebd55,0x3d800000,0xbcc43d6d,0xbd35bd35,0x3d6dbcc4,0xbd0ebd55,0x3d7bbc48,0xbc483d7b,0xbd55bd0e,
0xbc483d7b,0xbd0e3d55,0xbd553d0e,0xbd7b3c48,0xbd80,0x3cc4bd6d,0x3d35bd35,0x3d6dbcc4,0x3d7b3c48,0x3d553d0e,0x3d0e3d55,0x3c483d7b,0xbd800000,0xbd6dbcc4,0xbd35bd35,0xbcc4bd6d,
0x3c48bd7b,0x3d0ebd55,0x3d55bd0e,0x3d7bbc48,0x3d80,0xbcc43d6d,0xbd353d35,0xbd6d3cc4,0xbd7bbc48,0xbd55bd0e,0xbd0ebd55,0xbc48bd7b,0x3d800000,0x3d6d3cc4,0x3d353d35,0x3cc43d6d,
0x80003d80,0x80003d80,0x80003d80,0x80003d80,0x8000bd80,0x8000bd80,0x8000bd80,0x8000bd80,0x80003d80,0x80003d80,0x80003d80,0x80003d80,0x8000bd80,0x8000bd80,0x8000bd80,0x8000bd80,
0x80003d80,0x80003d80,0x80003d80,0x80003d80,0x8000bd80,0x8000bd80,0x8000bd80,0x8000bd80,0x80003d80,0x80003d80,0x80003d80,0x80003d80,0x8000bd80,0x8000bd80,0x8000bd80,0x8000bd80,
0xbd35bd35,0xbd353d35,0x3d353d35,0x3d35bd35,0x80003d80,0x3d800000,0x8000bd80,0xbd800000,0xbd35bd35,0xbd353d35,0x3d353d35,0x3d35bd35,0x80003d80,0x3d800000,0x8000bd80,0xbd800000,
0xbd35bd35,0xbd353d35,0x3d353d35,0x3d35bd35,0x80003d80,0x3d800000,0x8000bd80,0xbd800000,0xbd35bd35,0xbd353d35,0x3d353d35,0x3d35bd35,0x80003d80,0x3d800000,0x8000bd80,0xbd800000,
0x3d800000,0x3d6dbcc4,0x3d35bd35,0x3cc4bd6d,0xbd7b3c48,0xbd553d0e,0xbd0e3d55,0xbc483d7b,0x80003d80,0x3cc43d6d,0x3d353d35,0x3d6d3cc4,0xbc48bd7b,0xbd0ebd55,0xbd55bd0e,0xbd7bbc48,
0xbd800000,0xbd6d3cc4,0xbd353d35,0xbcc43d6d,0x3d7bbc48,0x3d55bd0e,0x3d0ebd55,0x3c48bd7b,0x8000bd80,0xbcc4bd6d,0xbd35bd35,0xbd6dbcc4,0x3c483d7b,0x3d0e3d55,0x3d553d0e,0x3d7b3c48,
0xbd0e3d55,0x3d7b3c48,0xbc48bd7b,0xbd553d0e,0x3d800000,0xbcc4bd6d,0xbd353d35,0x3d6d3cc4,0xbd55bd0e,0xbc483d7b,0x3d7bbc48,0xbd0ebd55,0x80003d80,0x3d6dbcc4,0xbd35bd35,0xbcc43d6d,
0x3d0ebd55,0xbd7bbc48,0x3c483d7b,0x3d55bd0e,0xbd800000,0x3cc43d6d,0x3d35bd35,0xbd6dbcc4,0x3d553d0e,0x3c48bd7b,0xbd7b3c48,0x3d0e3d55,0x8000bd80,0xbd6d3cc4,0x3d353d35,0x3cc4bd6d,
0x80003d80,0x3d353d35,0x3d800000,0x3d35bd35,0xbcc4bd6d,0xbd6dbcc4,0xbd6d3cc4,0xbcc43d6d,0x8000bd80,0xbd35bd35,0xbd800000,0xbd353d35,0x3cc43d6d,0x3d6d3cc4,0x3d6dbcc4,0x3cc4bd6d,
0x80003d80,0x3d353d35,0x3d800000,0x3d35bd35,0xbcc4bd6d,0xbd6dbcc4,0xbd6d3cc4,0xbcc43d6d,0x8000bd80,0xbd35bd35,0xbd800000,0xbd353d35,0x3cc43d6d,0x3d6d3cc4,0x3d6dbcc4,0x3cc4bd6d,
0xbd6dbcc4,0x3cc43d6d,0x3cc4bd6d,0xbd6d3cc4,0x80003d80,0x3d35bd35,0xbd800000,0x3d353d35,0x3d6d3cc4,0xbcc4bd6d,0xbcc43d6d,0x3d6dbcc4,0x8000bd80,0xbd353d35,0x3d800000,0xbd35bd35,
0xbd6dbcc4,0x3cc43d6d,0x3cc4bd6d,0xbd6d3cc4,0x80003d80,0x3d35bd35,0xbd800000,0x3d353d35,0x3d6d3cc4,0xbcc4bd6d,0xbcc43d6d,0x3d6dbcc4,0x8000bd80,0xbd353d35,0x3d800000,0xbd35bd35,
0x3d800000,0x3cc4bd6d,0xbd35bd35,0xbd6d3cc4,0xbd553d0e,0x3c483d7b,0x3d7b3c48,0x3d0ebd55,0x8000bd80,0xbd6dbcc4,0xbd353d35,0x3cc43d6d,0x3d0e3d55,0x3d7bbc48,0x3c48bd7b,0xbd55bd0e,
0xbd800000,0xbcc43d6d,0x3d353d35,0x3d6dbcc4,0x3d55bd0e,0xbc48bd7b,0xbd7bbc48,0xbd0e3d55,0x80003d80,0x3d6d3cc4,0x3d35bd35,0xbcc4bd6d,0xbd0ebd55,0xbd7b3c48,0xbc483d7b,0x3d553d0e,
0xbc483d7b,0x3d0ebd55,0xbd553d0e,0x3d7bbc48,0x3d800000,0xbd6dbcc4,0x3d353d35,0xbcc4bd6d,0x3d7b3c48,0xbd55bd0e,0x3d0e3d55,0xbc48bd7b,0x8000bd80,0xbcc43d6d,0x3d35bd35,0xbd6d3cc4,
0x3c48bd7b,0xbd0e3d55,0x3d55bd0e,0xbd7b3c48,0xbd800000,0x3d6d3cc4,0xbd35bd35,0x3cc43d6d,0xbd7bbc48,0x3d553d0e,0xbd0ebd55,0x3c483d7b,0x80003d80,0x3cc4bd6d,0xbd353d35,0x3d6dbcc4,
0x3d800000,0x3d800000,0x3d800000,0x3d800000,0xbd800000,0xbd800000,0xbd800000,0xbd800000,0x3d800000,0x3d800000,0x3d800000,0x3d800000,0xbd800000,0xbd800000,0xbd800000,0xbd800000,
0x3d800000,0x3d800000,0x3d800000,0x3d800000,0xbd800000,0xbd800000,0xbd800000,0xbd800000,0x3d800000,0x3d800000,0x3d800000,0x3d800000,0xbd800000,0xbd800000,0xbd800000,0xbd800000,
0xbd353d35,0x3d353d35,0x3d35bd35,0xbd35bd35,0x3d800000,0xbd80,0xbd800000,0x3d80,0xbd353d35,0x3d353d35,0x3d35bd35,0xbd35bd35,0x3d800000,0xbd80,0xbd800000,0x3d80,
0xbd353d35,0x3d353d35,0x3d35bd35,0xbd35bd35,0x3d800000,0xbd80,0xbd800000,0x3d80,0xbd353d35,0x3d353d35,0x3d35bd35,0xbd35bd35,0x3d800000,0xbd80,0xbd800000,0x3d80,
0xbd80,0xbcc4bd6d,0xbd35bd35,0xbd6dbcc4,0x3c483d7b,0x3d0e3d55,0x3d553d0e,0x3d7b3c48,0x3d800000,0x3d6dbcc4,0x3d35bd35,0x3cc4bd6d,0xbd7b3c48,0xbd553d0e,0xbd0e3d55,0xbc483d7b,
0x3d80,0x3cc43d6d,0x3d353d35,0x3d6d3cc4,0xbc48bd7b,0xbd0ebd55,0xbd55bd0e,0xbd7bbc48,0xbd800000,0xbd6d3cc4,0xbd353d35,0xbcc43d6d,0x3d7bbc48,0x3d55bd0e,0x3d0ebd55,0x3c48bd7b,
0x3d553d0e,0x3c48bd7b,0xbd7b3c48,0x3d0e3d55,0xbd80,0xbd6d3cc4,0x3d353d35,0x3cc4bd6d,0xbd0e3d55,0x3d7b3c48,0xbc48bd7b,0xbd553d0e,0x3d800000,0xbcc4bd6d,0xbd353d35,0x3d6d3cc4,
0xbd55bd0e,0xbc483d7b,0x3d7bbc48,0xbd0ebd55,0x3d80,0x3d6dbcc4,0xbd35bd35,0xbcc43d6d,0x3d0ebd55,0xbd7bbc48,0x3c483d7b,0x3d55bd0e,0xbd800000,0x3cc43d6d,0x3d35bd35,0xbd6dbcc4,
0x3d800000,0x3d35bd35,0xbd80,0xbd35bd35,0xbd6d3cc4,0xbcc43d6d,0x3cc43d6d,0x3d6d3cc4,0xbd800000,0xbd353d35,0x3d80,0x3d353d35,0x3d6dbcc4,0x3cc4bd6d,0xbcc4bd6d,0xbd6dbcc4,
0x3d800000,0x3d35bd35,0xbd80,0xbd35bd35,0xbd6d3cc4,0xbcc43d6d,0x3cc43d6d,0x3d6d3cc4,0xbd800000,0xbd353d35,0x3d80,0x3d353d35,0x3d6dbcc4,0x3cc4bd6d,0xbcc4bd6d,0xbd6dbcc4,
0xbcc43d6d,0x3d6dbcc4,0xbd6dbcc4,0x3cc43d6d,0x3d800000,0xbd35bd35,0x3d80,0x3d35bd35,0x3cc4bd6d,0xbd6d3cc4,0x3d6d3cc4,0xbcc4bd6d,0xbd800000,0x3d353d35,0xbd80,0xbd353d35,
0xbcc43d6d,0x3d6dbcc4,0xbd6dbcc4,0x3cc43d6d,0x3d800000,0xbd35bd35,0x3d80,0x3d35bd35,0x3cc4bd6d,0xbd6d3cc4,0x3d6d3cc4,0xbcc4bd6d,0xbd800000,0x3d353d35,0xbd80,0xbd353d35,
0xbd80,0xbd6dbcc4,0xbd353d35,0x3cc43d6d,0x3d0e3d55,0x3d7bbc48,0x3c48bd7b,0xbd55bd0e,0xbd800000,0xbcc43d6d,0x3d353d35,0x3d6dbcc4,0x3d55bd0e,0xbc48bd7b,0xbd7bbc48,0xbd0e3d55,
0x3d80,0x3d6d3cc4,0x3d35bd35,0xbcc4bd6d,0xbd0ebd55,0xbd7b3c48,0xbc483d7b,0x3d553d0e,0x3d800000,0x3cc4bd6d,0xbd35bd35,0xbd6d3cc4,0xbd553d0e,0x3c483d7b,0x3d7b3c48,0x3d0ebd55,
0x3d7b3c48,0xbd55bd0e,0x3d0e3d55,0xbc48bd7b,0xbd80,0xbcc43d6d,0x3d35bd35,0xbd6d3cc4,0x3c48bd7b,0xbd0e3d55,0x3d55bd0e,0xbd7b3c48,0xbd800000,0x3d6d3cc4,0xbd35bd35,0x3cc43d6d,
0xbd7bbc48,0x3d553d0e,0xbd0ebd55,0x3c483d7b,0x3d80,0x3cc4bd6d,0xbd353d35,0x3d6dbcc4,0xbc483d7b,0x3d0ebd55,0xbd553d0e,0x3d7bbc48,0x3d800000,0xbd6dbcc4,0x3d353d35,0xbcc4bd6d,
0x80003d80,0x8000bd80,0x80003d80,0x8000bd80,0xbd800000,0x3d800000,0xbd800000,0x3d800000,0x80003d80,0x8000bd80,0x80003d80,0x8000bd80,0xbd800000,0x3d800000,0xbd800000,0x3d800000,
0x80003d80,0x8000bd80,0x80003d80,0x8000bd80,0xbd800000,0x3d800000,0xbd800000,0x3d800000,0x80003d80,0x8000bd80,0x80003d80,0x8000bd80,0xbd800000,0x3d800000,0xbd800000,0x3d800000,
0xbd353d35,0xbd35bd35,0x3d35bd35,0x3d353d35,0x80003d80,0xbd800000,0x8000bd80,0x3d800000,0xbd353d35,0xbd35bd35,0x3d35bd35,0x3d353d35,0x80003d80,0xbd800000,0x8000bd80,0x3d800000,
0xbd353d35,0xbd35bd35,0x3d35bd35,0x3d353d35,0x80003d80,0xbd800000,0x8000bd80,0x3d800000,0xbd353d35,0xbd35bd35,0x3d35bd35,0x3d353d35,0x80003d80,0xbd800000,0x8000bd80,0x3d800000,
0x3d800000,0xbd6d3cc4,0x3d35bd35,0xbcc43d6d,0x3c483d7b,0xbd0ebd55,0x3d553d0e,0xbd7bbc48,0x80003d80,0xbcc4bd6d,0x3d353d35,0xbd6dbcc4,0xbd7b3c48,0x3d55bd0e,0xbd0e3d55,0x3c48bd7b,
0xbd800000,0x3d6dbcc4,0xbd353d35,0x3cc4bd6d,0xbc48bd7b,0x3d0e3d55,0xbd55bd0e,0x3d7b3c48,0x8000bd80,0x3cc43d6d,0xbd35bd35,0x3d6d3cc4,0x3d7bbc48,0xbd553d0e,0x3d0ebd55,0xbc483d7b,
0x3d553d0e,0xbc483d7b,0xbd7b3c48,0xbd0ebd55,0x3d800000,0x3cc43d6d,0xbd353d35,0xbd6dbcc4,0xbd0e3d55,0xbd7bbc48,0xbc48bd7b,0x3d55bd0e,0x80003d80,0xbd6d3cc4,0xbd35bd35,0x3cc4bd6d,
0xbd55bd0e,0x3c48bd7b,0x3d7bbc48,0x3d0e3d55,0xbd800000,0xbcc4bd6d,0x3d35bd35,0x3d6d3cc4,0x3d0ebd55,0x3d7b3c48,0x3c483d7b,0xbd553d0e,0x8000bd80,0x3d6dbcc4,0x3d353d35,0xbcc43d6d,
0x80003d80,0xbd35bd35,0x3d800000,0xbd353d35,0xbd6d3cc4,0x3cc4bd6d,0x3cc43d6d,0xbd6dbcc4,0x8000bd80,0x3d353d35,0xbd800000,0x3d35bd35,0x3d6dbcc4,0xbcc43d6d,0xbcc4bd6d,0x3d6d3cc4,
0x80003d80,0xbd35bd35,0x3d800000,0xbd353d35,0xbd6d3cc4,0x3cc4bd6d,0x3cc43d6d,0xbd6dbcc4,0x8000bd80,0x3d353d35,0xbd800000,0x3d35bd35,0x3d6dbcc4,0xbcc43d6d,0xbcc4bd6d,0x3d6d3cc4,
0xbcc43d6d,0xbd6d3cc4,0xbd6dbcc4,0xbcc4bd6d,0x80003d80,0xbd353d35,0xbd800000,0xbd35bd35,0x3cc4bd6d,0x3d6dbcc4,0x3d6d3cc4,0x3cc43d6d,0x8000bd80,0x3d35bd35,0x3d800000,0x3d353d35,
0xbcc43d6d,0xbd6d3cc4,0xbd6dbcc4,0xbcc4bd6d,0x80003d80,0xbd353d35,0xbd800000,0xbd35bd35,0x3cc4bd6d,0x3d6dbcc4,0x3d6d3cc4,0x3cc43d6d,0x8000bd80,0x3d35bd35,0x3d800000,0x3d353d35,
0x3d800000,0xbcc43d6d,0xbd35bd35,0x3d6dbcc4,0x3d0e3d55,0xbd7b3c48,0x3c48bd7b,0x3d553d0e,0x8000bd80,0x3d6d3cc4,0xbd353d35,0xbcc4bd6d,0x3d55bd0e,0x3c483d7b,0xbd7bbc48,0x3d0ebd55,
0xbd800000,0x3cc4bd6d,0x3d353d35,0xbd6d3cc4,0xbd0ebd55,0x3d7bbc48,0xbc483d7b,0xbd55bd0e,0x80003d80,0xbd6dbcc4,0x3d35bd35,0x3cc43d6d,0xbd553d0e,0xbc48bd7b,0x3d7b3c48,0xbd0e3d55,
0x3d7b3c48,0x3d553d0e,0x3d0e3d55,0x3c483d7b,0x3d800000,0x3d6d3cc4,0x3d353d35,0x3cc43d6d,0x3c48bd7b,0x3d0ebd55,0x3d55bd0e,0x3d7bbc48,0x8000bd80,0x3cc4bd6d,0x3d35bd35,0x3d6dbcc4,
0xbd7bbc48,0xbd55bd0e,0xbd0ebd55,0xbc48bd7b,0xbd800000,0xbd6dbcc4,0xbd35bd35,0xbcc4bd6d,0xbc483d7b,0xbd0e3d55,0xbd553d0e,0xbd7b3c48,0x80003d80,0xbcc43d6d,0xbd353d35,0xbd6d3cc4,
0x3d800000,0xbd800000,0x3d800000,0xbd800000,0x3d80,0xbd80,0x3d80,0xbd80,0x3d800000,0xbd800000,0x3d800000,0xbd800000,0x3d80,0xbd80,0x3d80,0xbd80,
0x3d800000,0xbd800000,0x3d800000,0xbd800000,0x3d80,0xbd80,0x3d80,0xbd80,0x3d800000,0xbd800000,0x3d800000,0xbd800000,0x3d80,0xbd80,0x3d80,0xbd80,
0x3d353d35,0xbd353d35,0xbd35bd35,0x3d35bd35,0x3d800000,0x3d80,0xbd800000,0xbd80,0x3d353d35,0xbd353d35,0xbd35bd35,0x3d35bd35,0x3d800000,0x3d80,0xbd800000,0xbd80,
0x3d353d35,0xbd353d35,0xbd35bd35,0x3d35bd35,0x3d800000,0x3d80,0xbd800000,0xbd80,0x3d353d35,0xbd353d35,0xbd35bd35,0x3d35bd35,0x3d800000,0x3d80,0xbd800000,0xbd80,
0xbd80,0x3cc43d6d,0xbd35bd35,0x3d6d3cc4,0x3d7bbc48,0xbd553d0e,0x3d0ebd55,0xbc483d7b,0x3d800000,0xbd6d3cc4,0x3d35bd35,0xbcc43d6d,0x3c483d7b,0xbd0ebd55,0x3d553d0e,0xbd7bbc48,
0x3d80,0xbcc4bd6d,0x3d353d35,0xbd6dbcc4,0xbd7b3c48,0x3d55bd0e,0xbd0e3d55,0x3c48bd7b,0xbd800000,0x3d6dbcc4,0xbd353d35,0x3cc4bd6d,0xbc48bd7b,0x3d0e3d55,0xbd55bd0e,0x3d7b3c48,
0x3d0ebd55,0x3d7b3c48,0x3c483d7b,0xbd553d0e,0xbd80,0x3d6dbcc4,0x3d353d35,0xbcc43d6d,0x3d553d0e,0xbc483d7b,0xbd7b3c48,0xbd0ebd55,0x3d800000,0x3cc43d6d,0xbd353d35,0xbd6dbcc4,
0xbd0e3d55,0xbd7bbc48,0xbc48bd7b,0x3d55bd0e,0x3d80,0xbd6d3cc4,0xbd35bd35,0x3cc4bd6d,0xbd55bd0e,0x3c48bd7b,0x3d7bbc48,0x3d0e3d55,0xbd800000,0xbcc4bd6d,0x3d35bd35,0x3d6d3cc4,
0x3d800000,0xbd353d35,0xbd80,0x3d353d35,0x3cc43d6d,0xbd6dbcc4,0x3d6dbcc4,0xbcc43d6d,0xbd800000,0x3d35bd35,0x3d80,0xbd35bd35,0xbcc4bd6d,0x3d6d3cc4,0xbd6d3cc4,0x3cc4bd6d,
0x3d800000,0xbd353d35,0xbd80,0x3d353d35,0x3cc43d6d,0xbd6dbcc4,0x3d6dbcc4,0xbcc43d6d,0xbd800000,0x3d35bd35,0x3d80,0xbd35bd35,0xbcc4bd6d,0x3d6d3cc4,0xbd6d3cc4,0x3cc4bd6d,
0x3d6d3cc4,0x3cc43d6d,0xbcc43d6d,0xbd6d3cc4,0x3d800000,0x3d353d35,0x3d80,0xbd353d35,0xbd6dbcc4,0xbcc4bd6d,0x3cc4bd6d,0x3d6dbcc4,0xbd800000,0xbd35bd35,0xbd80,0x3d35bd35,
0x3d6d3cc4,0x3cc43d6d,0xbcc43d6d,0xbd6d3cc4,0x3d800000,0x3d353d35,0x3d80,0xbd353d35,0xbd6dbcc4,0xbcc4bd6d,0x3cc4bd6d,0x3d6dbcc4,0xbd800000,0xbd35bd35,0xbd80,0x3d35bd35,
0xbd80,0x3d6d3cc4,0xbd353d35,0xbcc4bd6d,0x3d55bd0e,0x3c483d7b,0xbd7bbc48,0x3d0ebd55,0xbd800000,0x3cc4bd6d,0x3d353d35,0xbd6d3cc4,0xbd0ebd55,0x3d7bbc48,0xbc483d7b,0xbd55bd0e,
0x3d80,0xbd6dbcc4,0x3d35bd35,0x3cc43d6d,0xbd553d0e,0xbc48bd7b,0x3d7b3c48,0xbd0e3d55,0x3d800000,0xbcc43d6d,0xbd35bd35,0x3d6dbcc4,0x3d0e3d55,0xbd7b3c48,0x3c48bd7b,0x3d553d0e,
0x3c48bd7b,0x3d0ebd55,0x3d55bd0e,0x3d7bbc48,0xbd80,0x3cc4bd6d,0x3d35bd35,0x3d6dbcc4,0xbd7bbc48,0xbd55bd0e,0xbd0ebd55,0xbc48bd7b,0xbd800000,0xbd6dbcc4,0xbd35bd35,0xbcc4bd6d,
0xbc483d7b,0xbd0e3d55,0xbd553d0e,0xbd7b3c48,0x3d80,0xbcc43d6d,0xbd353d35,0xbd6d3cc4,0x3d7b3c48,0x3d553d0e,0x3d0e3d55,0x3c483d7b,0x3d800000,0x3d6d3cc4,0x3d353d35,0x3cc43d6d,
0x3d80,0x3d80,0x3d80,0x3d80,0x3d80,0x3d80,0x3d80,0x3d80,0x3d80,0x3d80,0x3d80,0x3d80,0x3d80,0x3d80,0x3d80,0x3d80,
0x3d80,0x3d80,0x3d80,0x3d80,0x3d80,0x3d80,0x3d80,0x3d80,0x3d80,0x3d80,0x3d80,0x3d80,0x3d80,0x3d80,0x3d80,0x3d80,
0xbd353d35,0xbd553d0e,0xbd6d3cc4,0xbd7b3c48,0x3d80,0xbc483d7b,0xbcc43d6d,0xbd0e3d55,0xbd35bd35,0xbd0ebd55,0xbcc4bd6d,0xbc48bd7b,0xbd800000,0xbd7bbc48,0xbd6dbcc4,0xbd55bd0e,
0x3d35bd35,0x3d55bd0e,0x3d6dbcc4,0x3d7bbc48,0xbd80,0x3c48bd7b,0x3cc4bd6d,0x3d0ebd55,0x3d353d35,0x3d0e3d55,0x3cc43d6d,0x3c483d7b,0x3d800000,0x3d7b3c48,0x3d6d3cc4,0x3d553d0e,
0xbd80,0x3cc4bd6d,0x3d35bd35,0x3d6dbcc4,0x3d800000,0x3d6d3cc4,0x3d353d35,0x3cc43d6d,0x3d80,0xbcc43d6d,0xbd353d35,0xbd6d3cc4,0xbd800000,0xbd6dbcc4,0xbd35bd35,0xbcc4bd6d,
0xbd80,0x3cc4bd6d,0x3d35bd35,0x3d6dbcc4,0x3d800000,0x3d6d3cc4,0x3d353d35,0x3cc43d6d,0x3d80,0xbcc43d6d,0xbd353d35,0xbd6d3cc4,0xbd800000,0xbd6dbcc4,0xbd35bd35,0xbcc4bd6d,
0xbd353d35,0xbd7b3c48,0xbd6dbcc4,0xbd0ebd55,0x3d800000,0x3d553d0e,0x3cc43d6d,0xbc483d7b,0xbd35bd35,0xbc48bd7b,0x3cc4bd6d,0x3d55bd0e,0x3d80,0xbd0e3d55,0xbd6d3cc4,0xbd7bbc48,
0x3d35bd35,0x3d7bbc48,0x3d6d3cc4,0x3d0e3d55,0xbd800000,0xbd55bd0e,0xbcc4bd6d,0x3c48bd7b,0x3d353d35,0x3c483d7b,0xbcc43d6d,0xbd553d0e,0xbd80,0x3d0ebd55,0x3d6dbcc4,0x3d7b3c48,
0x3d80,0xbd353d35,0xbd800000,0xbd35bd35,0xbd80,0x3d35bd35,0x3d800000,0x3d353d35,0x3d80,0xbd353d35,0xbd800000,0xbd35bd35,0xbd80,0x3d35bd35,0x3d800000,0x3d353d35,
0x3d80,0xbd353d35,0xbd800000,0xbd35bd35,0xbd80,0x3d35bd35,0x3d800000,0x3d353d35,0x3d80,0xbd353d35,0xbd800000,0xbd35bd35,0xbd80,0x3d35bd35,0x3d800000,0x3d353d35,
0xbd353d35,0xbd7bbc48,0xbcc4bd6d,0x3d0ebd55,0xbd80,0x3d55bd0e,0x3d6d3cc4,0x3c483d7b,0xbd35bd35,0x3c48bd7b,0x3d6dbcc4,0x3d553d0e,0x3d800000,0x3d0e3d55,0xbcc43d6d,0xbd7b3c48,
0x3d35bd35,0x3d7b3c48,0x3cc43d6d,0xbd0e3d55,0x3d80,0xbd553d0e,0xbd6dbcc4,0xbc48bd7b,0x3d353d35,0xbc483d7b,0xbd6d3cc4,0xbd55bd0e,0xbd800000,0xbd0ebd55,0x3cc4bd6d,0x3d7bbc48,
0xbd80,0x3d6dbcc4,0x3d353d35,0xbcc43d6d,0xbd800000,0xbcc4bd6d,0x3d35bd35,0x3d6d3cc4,0x3d80,0xbd6d3cc4,0xbd35bd35,0x3cc4bd6d,0x3d800000,0x3cc43d6d,0xbd353d35,0xbd6dbcc4,
0xbd80,0x3d6dbcc4,0x3d353d35,0xbcc43d6d,0xbd800000,0xbcc4bd6d,0x3d35bd35,0x3d6d3cc4,0x3d80,0xbd6d3cc4,0xbd35bd35,0x3cc4bd6d,0x3d800000,0x3cc43d6d,0xbd353d35,0xbd6dbcc4,
0xbd353d35,0xbd55bd0e,0x3cc4bd6d,0x3d7b3c48,0xbd800000,0xbc48bd7b,0x3d6dbcc4,0x3d0e3d55,0xbd35bd35,0x3d0ebd55,0x3d6d3cc4,0xbc483d7b,0xbd80,0x3d7bbc48,0x3cc43d6d,0xbd553d0e,
0x3d35bd35,0x3d553d0e,0xbcc43d6d,0xbd7bbc48,0x3d800000,0x3c483d7b,0xbd6d3cc4,0xbd0ebd55,0x3d353d35,0xbd0e3d55,0xbd6dbcc4,0x3c48bd7b,0x3d80,0xbd7b3c48,0xbcc4bd6d,0x3d55bd0e,
0xbd800000,0xbd800000,0xbd800000,0xbd800000,0xbd800000,0xbd800000,0xbd800000,0xbd800000,0xbd800000,0xbd800000,0xbd800000,0xbd800000,0xbd800000,0xbd800000,0xbd800000,0xbd800000,
0xbd800000,0xbd800000,0xbd800000,0xbd800000,0xbd800000,0xbd800000,0xbd800000,0xbd800000,0xbd800000,0xbd800000,0xbd800000,0xbd800000,0xbd800000,0xbd800000,0xbd800000,0xbd800000,
0xbd35bd35,0xbd0ebd55,0xbcc4bd6d,0xbc48bd7b,0xbd800000,0xbd7bbc48,0xbd6dbcc4,0xbd55bd0e,0x3d35bd35,0x3d55bd0e,0x3d6dbcc4,0x3d7bbc48,0x8000bd80,0x3c48bd7b,0x3cc4bd6d,0x3d0ebd55,
0x3d353d35,0x3d0e3d55,0x3cc43d6d,0x3c483d7b,0x3d800000,0x3d7b3c48,0x3d6d3cc4,0x3d553d0e,0xbd353d35,0xbd553d0e,0xbd6d3cc4,0xbd7b3c48,0x80003d80,0xbc483d7b,0xbcc43d6d,0xbd0e3d55,
0x3d800000,0x3d6d3cc4,0x3d353d35,0x3cc43d6d,0x80003d80,0xbcc43d6d,0xbd353d35,0xbd6d3cc4,0xbd800000,0xbd6dbcc4,0xbd35bd35,0xbcc4bd6d,0x8000bd80,0x3cc4bd6d,0x3d35bd35,0x3d6dbcc4,
0x3d800000,0x3d6d3cc4,0x3d353d35,0x3cc43d6d,0x80003d80,0xbcc43d6d,0xbd353d35,0xbd6d3cc4,0xbd800000,0xbd6dbcc4,0xbd35bd35,0xbcc4bd6d,0x8000bd80,0x3cc4bd6d,0x3d35bd35,0x3d6dbcc4,
0xbd35bd35,0xbc48bd7b,0x3cc4bd6d,0x3d55bd0e,0x80003d80,0xbd0e3d55,0xbd6d3cc4,0xbd7bbc48,0x3d35bd35,0x3d7bbc48,0x3d6d3cc4,0x3d0e3d55,0xbd800000,0xbd55bd0e,0xbcc4bd6d,0x3c48bd7b,
0x3d353d35,0x3c483d7b,0xbcc43d6d,0xbd553d0e,0x8000bd80,0x3d0ebd55,0x3d6dbcc4,0x3d7b3c48,0xbd353d35,0xbd7b3c48,0xbd6dbcc4,0xbd0ebd55,0x3d800000,0x3d553d0e,0x3cc43d6d,0xbc483d7b,
0xbd800000,0xbd35bd35,0x8000bd80,0x3d35bd35,0x3d800000,0x3d353d35,0x80003d80,0xbd353d35,0xbd800000,0xbd35bd35,0x8000bd80,0x3d35bd35,0x3d800000,0x3d353d35,0x80003d80,0xbd353d35,
0xbd800000,0xbd35bd35,0x8000bd80,0x3d35bd35,0x3d800000,0x3d353d35,0x80003d80,0xbd353d35,0xbd800000,0xbd35bd35,0x8000bd80,0x3d35bd35,0x3d800000,0x3d353d35,0x80003d80,0xbd353d35,
0xbd35bd35,0x3c48bd7b,0x3d6dbcc4,0x3d553d0e,0x3d800000,0x3d0e3d55,0xbcc43d6d,0xbd7b3c48,0x3d35bd35,0x3d7b3c48,0x3cc43d6d,0xbd0e3d55,0x80003d80,0xbd553d0e,0xbd6dbcc4,0xbc48bd7b,
0x3d353d35,0xbc483d7b,0xbd6d3cc4,0xbd55bd0e,0xbd800000,0xbd0ebd55,0x3cc4bd6d,0x3d7bbc48,0xbd353d35,0xbd7bbc48,0xbcc4bd6d,0x3d0ebd55,0x8000bd80,0x3d55bd0e,0x3d6d3cc4,0x3c483d7b,
0x3d800000,0x3cc43d6d,0xbd353d35,0xbd6dbcc4,0x8000bd80,0x3d6dbcc4,0x3d353d35,0xbcc43d6d,0xbd800000,0xbcc4bd6d,0x3d35bd35,0x3d6d3cc4,0x80003d80,0xbd6d3cc4,0xbd35bd35,0x3cc4bd6d,
0x3d800000,0x3cc43d6d,0xbd353d35,0xbd6dbcc4,0x8000bd80,0x3d6dbcc4,0x3d353d35,0xbcc43d6d,0xbd800000,0xbcc4bd6d,0x3d35bd35,0x3d6d3cc4,0x80003d80,0xbd6d3cc4,0xbd35bd35,0x3cc4bd6d,
0xbd35bd35,0x3d0ebd55,0x3d6d3cc4,0xbc483d7b,0x8000bd80,0x3d7bbc48,0x3cc43d6d,0xbd553d0e,0x3d35bd35,0x3d553d0e,0xbcc43d6d,0xbd7bbc48,0x3d800000,0x3c483d7b,0xbd6d3cc4,0xbd0ebd55,
0x3d353d35,0xbd0e3d55,0xbd6dbcc4,0x3c48bd7b,0x80003d80,0xbd7b3c48,0xbcc4bd6d,0x3d55bd0e,0xbd353d35,0xbd55bd0e,0x3cc4bd6d,0x3d7b3c48,0xbd800000,0xbc48bd7b,0x3d6dbcc4,0x3d0e3d55,
0x3d80,0xbd800000,0xbd80,0x3d800000,0x3d80,0xbd800000,0xbd80,0x3d800000,0x3d80,0xbd800000,0xbd80,0x3d800000,0x3d80,0xbd800000,0xbd80,0x3d800000,
0x3d80,0xbd800000,0xbd80,0x3d800000,0x3d80,0xbd800000,0xbd80,0x3d800000,0x3d80,0xbd800000,0xbd80,0x3d800000,0x3d80,0xbd800000,0xbd80,0x3d800000,
0xbd353d35,0xbd0ebd55,0x3d6dbcc4,0x3c483d7b,0x3d80,0xbd7bbc48,0x3cc4bd6d,0x3d553d0e,0xbd35bd35,0x3d55bd0e,0x3cc43d6d,0xbd7b3c48,0xbd800000,0x3c48bd7b,0x3d6d3cc4,0xbd0e3d55,
0x3d35bd35,0x3d0e3d55,0xbd6d3cc4,0xbc48bd7b,0xbd80,0x3d7b3c48,0xbcc43d6d,0xbd55bd0e,0x3d353d35,0xbd553d0e,0xbcc4bd6d,0x3d7bbc48,0x3d800000,0xbc483d7b,0xbd6dbcc4,0x3d0ebd55,
0xbd80,0x3d6d3cc4,0xbd353d35,0xbcc4bd6d,0x3d800000,0xbcc43d6d,0xbd35bd35,0x3d6dbcc4,0x3d80,0xbd6dbcc4,0x3d35bd35,0x3cc43d6d,0xbd800000,0x3cc4bd6d,0x3d353d35,0xbd6d3cc4,
0xbd80,0x3d6d3cc4,0xbd353d35,0xbcc4bd6d,0x3d800000,0xbcc43d6d,0xbd35bd35,0x3d6dbcc4,0x3d80,0xbd6dbcc4,0x3d35bd35,0x3cc43d6d,0xbd800000,0x3cc4bd6d,0x3d353d35,0xbd6d3cc4,
0xbd353d35,0xbc48bd7b,0x3d6d3cc4,0xbd553d0e,0x3d800000,0xbd0e3d55,0xbcc4bd6d,0x3d7b3c48,0xbd35bd35,0x3d7bbc48,0xbcc43d6d,0xbd0ebd55,0x3d80,0xbd55bd0e,0x3d6dbcc4,0xbc483d7b,
0x3d35bd35,0x3c483d7b,0xbd6dbcc4,0x3d55bd0e,0xbd800000,0x3d0ebd55,0x3cc43d6d,0xbd7bbc48,0x3d353d35,0xbd7b3c48,0x3cc4bd6d,0x3d0e3d55,0xbd80,0x3d553d0e,0xbd6d3cc4,0x3c48bd7b,
0x3d80,0xbd35bd35,0x3d800000,0xbd353d35,0xbd80,0x3d353d35,0xbd800000,0x3d35bd35,0x3d80,0xbd35bd35,0x3d800000,0xbd353d35,0xbd80,0x3d353d35,0xbd800000,0x3d35bd35,
0x3d80,0xbd35bd35,0x3d800000,0xbd353d35,0xbd80,0x3d353d35,0xbd800000,0x3d35bd35,0x3d80,0xbd35bd35,0x3d800000,0xbd353d35,0xbd80,0x3d353d35,0xbd800000,0x3d35bd35,
0xbd353d35,0x3c48bd7b,0x3cc43d6d,0xbd55bd0e,0xbd80,0x3d0e3d55,0xbd6dbcc4,0x3d7bbc48,0xbd35bd35,0x3d7b3c48,0xbd6d3cc4,0x3d0ebd55,0x3d800000,0xbd553d0e,0x3cc4bd6d,0x3c483d7b,
0x3d35bd35,0xbc483d7b,0xbcc4bd6d,0x3d553d0e,0x3d80,0xbd0ebd55,0x3d6d3cc4,0xbd7b3c48,0x3d353d35,0xbd7bbc48,0x3d6dbcc4,0xbd0e3d55,0xbd800000,0x3d55bd0e,0xbcc43d6d,0xbc48bd7b,
0xbd80,0x3cc43d6d,0xbd35bd35,0x3d6d3cc4,0xbd800000,0x3d6dbcc4,0xbd353d35,0x3cc4bd6d,0x3d80,0xbcc4bd6d,0x3d353d35,0xbd6dbcc4,0x3d800000,0xbd6d3cc4,0x3d35bd35,0xbcc43d6d,
0xbd80,0x3cc43d6d,0xbd35bd35,0x3d6d3cc4,0xbd800000,0x3d6dbcc4,0xbd353d35,0x3cc4bd6d,0x3d80,0xbcc4bd6d,0x3d353d35,0xbd6dbcc4,0x3d800000,0xbd6d3cc4,0x3d35bd35,0xbcc43d6d,
0xbd353d35,0x3d0ebd55,0xbcc43d6d,0x3c48bd7b,0xbd800000,0x3d7bbc48,0xbd6d3cc4,0x3d55bd0e,0xbd35bd35,0x3d553d0e,0xbd6dbcc4,0x3d7b3c48,0xbd80,0x3c483d7b,0xbcc4bd6d,0x3d0e3d55,
0x3d35bd35,0xbd0e3d55,0x3cc4bd6d,0xbc483d7b,0x3d800000,0xbd7b3c48,0x3d6dbcc4,0xbd553d0e,0x3d353d35,0xbd55bd0e,0x3d6d3cc4,0xbd7bbc48,0x3d80,0xbc48bd7b,0x3cc43d6d,0xbd0ebd55,
0xbd800000,0x8000bd80,0x3d800000,0x80003d80,0xbd800000,0x8000bd80,0x3d800000,0x80003d80,0xbd800000,0x8000bd80,0x3d800000,0x80003d80,0xbd800000,0x8000bd80,0x3d800000,0x80003d80,
0xbd800000,0x8000bd80,0x3d800000,0x80003d80,0xbd800000,0x8000bd80,0x3d800000,0x80003d80,0xbd800000,0x8000bd80,0x3d800000,0x80003d80,0xbd800000,0x8000bd80,0x3d800000,0x80003d80,
0xbd35bd35,0x3d55bd0e,0x3cc43d6d,0xbd7b3c48,0xbd800000,0x3c48bd7b,0x3d6d3cc4,0xbd0e3d55,0x3d35bd35,0x3d0e3d55,0xbd6d3cc4,0xbc48bd7b,0x8000bd80,0x3d7b3c48,0xbcc43d6d,0xbd55bd0e,
0x3d353d35,0xbd553d0e,0xbcc4bd6d,0x3d7bbc48,0x3d800000,0xbc483d7b,0xbd6dbcc4,0x3d0ebd55,0xbd353d35,0xbd0ebd55,0x3d6dbcc4,0x3c483d7b,0x80003d80,0xbd7bbc48,0x3cc4bd6d,0x3d553d0e,
0x3d800000,0xbcc43d6d,0xbd35bd35,0x3d6dbcc4,0x80003d80,0xbd6dbcc4,0x3d35bd35,0x3cc43d6d,0xbd800000,0x3cc4bd6d,0x3d353d35,0xbd6d3cc4,0x8000bd80,0x3d6d3cc4,0xbd353d35,0xbcc4bd6d,
0x3d800000,0xbcc43d6d,0xbd35bd35,0x3d6dbcc4,0x80003d80,0xbd6dbcc4,0x3d35bd35,0x3cc43d6d,0xbd800000,0x3cc4bd6d,0x3d353d35,0xbd6d3cc4,0x8000bd80,0x3d6d3cc4,0xbd353d35,0xbcc4bd6d,
0xbd35bd35,0x3d7bbc48,0xbcc43d6d,0xbd0ebd55,0x80003d80,0xbd55bd0e,0x3d6dbcc4,0xbc483d7b,0x3d35bd35,0x3c483d7b,0xbd6dbcc4,0x3d55bd0e,0xbd800000,0x3d0ebd55,0x3cc43d6d,0xbd7bbc48,
0x3d353d35,0xbd7b3c48,0x3cc4bd6d,0x3d0e3d55,0x8000bd80,0x3d553d0e,0xbd6d3cc4,0x3c48bd7b,0xbd353d35,0xbc48bd7b,0x3d6d3cc4,0xbd553d0e,0x3d800000,0xbd0e3d55,0xbcc4bd6d,0x3d7b3c48,
0xbd800000,0x3d35bd35,0x80003d80,0xbd35bd35,0x3d800000,0xbd353d35,0x8000bd80,0x3d353d35,0xbd800000,0x3d35bd35,0x80003d80,0xbd35bd35,0x3d800000,0xbd353d35,0x8000bd80,0x3d353d35,
0xbd800000,0x3d35bd35,0x80003d80,0xbd35bd35,0x3d800000,0xbd353d35,0x8000bd80,0x3d353d35,0xbd800000,0x3d35bd35,0x80003d80,0xbd35bd35,0x3d800000,0xbd353d35,0x8000bd80,0x3d353d35,
0xbd35bd35,0x3d7b3c48,0xbd6d3cc4,0x3d0ebd55,0x3d800000,0xbd553d0e,0x3cc4bd6d,0x3c483d7b,0x3d35bd35,0xbc483d7b,0xbcc4bd6d,0x3d553d0e,0x80003d80,0xbd0ebd55,0x3d6d3cc4,0xbd7b3c48,
0x3d353d35,0xbd7bbc48,0x3d6dbcc4,0xbd0e3d55,0xbd800000,0x3d55bd0e,0xbcc43d6d,0xbc48bd7b,0xbd353d35,0x3c48bd7b,0x3cc43d6d,0xbd55bd0e,0x8000bd80,0x3d0e3d55,0xbd6dbcc4,0x3d7bbc48,
0x3d800000,0xbd6d3cc4,0x3d35bd35,0xbcc43d6d,0x8000bd80,0x3cc43d6d,0xbd35bd35,0x3d6d3cc4,0xbd800000,0x3d6dbcc4,0xbd353d35,0x3cc4bd6d,0x80003d80,0xbcc4bd6d,0x3d353d35,0xbd6dbcc4,
0x3d800000,0xbd6d3cc4,0x3d35bd35,0xbcc43d6d,0x8000bd80,0x3cc43d6d,0xbd35bd35,0x3d6d3cc4,0xbd800000,0x3d6dbcc4,0xbd353d35,0x3cc4bd6d,0x80003d80,0xbcc4bd6d,0x3d353d35,0xbd6dbcc4,
0xbd35bd35,0x3d553d0e,0xbd6dbcc4,0x3d7b3c48,0x8000bd80,0x3c483d7b,0xbcc4bd6d,0x3d0e3d55,0x3d35bd35,0xbd0e3d55,0x3cc4bd6d,0xbc483d7b,0x3d800000,0xbd7b3c48,0x3d6dbcc4,0xbd553d0e,
0x3d353d35,0xbd55bd0e,0x3d6d3cc4,0xbd7bbc48,0x80003d80,0xbc48bd7b,0x3cc43d6d,0xbd0ebd55,0xbd353d35,0x3d0ebd55,0xbcc43d6d,0x3c48bd7b,0xbd800000,0x3d7bbc48,0xbd6d3cc4,0x3d55bd0e,
0x3d80,0xbd80,0x3d80,0xbd80,0x3d80,0xbd80,0x3d80,0xbd80,0x3d80,0xbd80,0x3d80,0xbd80,0x3d80,0xbd80,0x3d80,0xbd80,
0x3d80,0xbd80,0x3d80,0xbd80,0x3d80,0xbd80,0x3d80,0xbd80,0x3d80,0xbd80,0x3d80,0xbd80,0x3d80,0xbd80,0x3d80,0xbd80,
0xbd353d35,0x3d55bd0e,0xbd6d3cc4,0x3d7bbc48,0x3d80,0x3c48bd7b,0xbcc43d6d,0x3d0ebd55,0xbd35bd35,0x3d0e3d55,0xbcc4bd6d,0x3c483d7b,0xbd800000,0x3d7b3c48,0xbd6dbcc4,0x3d553d0e,
0x3d35bd35,0xbd553d0e,0x3d6dbcc4,0xbd7b3c48,0xbd80,0xbc483d7b,0x3cc4bd6d,0xbd0e3d55,0x3d353d35,0xbd0ebd55,0x3cc43d6d,0xbc48bd7b,0x3d800000,0xbd7bbc48,0x3d6d3cc4,0xbd55bd0e,
0xbd80,0xbcc43d6d,0x3d35bd35,0xbd6d3cc4,0x3d800000,0xbd6dbcc4,0x3d353d35,0xbcc4bd6d,0x3d80,0x3cc4bd6d,0xbd353d35,0x3d6dbcc4,0xbd800000,0x3d6d3cc4,0xbd35bd35,0x3cc43d6d,
0xbd80,0xbcc43d6d,0x3d35bd35,0xbd6d3cc4,0x3d800000,0xbd6dbcc4,0x3d353d35,0xbcc4bd6d,0x3d80,0x3cc4bd6d,0xbd353d35,0x3d6dbcc4,0xbd800000,0x3d6d3cc4,0xbd35bd35,0x3cc43d6d,
0xbd353d35,0x3d7bbc48,0xbd6dbcc4,0x3d0e3d55,0x3d800000,0xbd55bd0e,0x3cc43d6d,0x3c48bd7b,0xbd35bd35,0x3c483d7b,0x3cc4bd6d,0xbd553d0e,0x3d80,0x3d0ebd55,0xbd6d3cc4,0x3d7b3c48,
0x3d35bd35,0xbd7b3c48,0x3d6d3cc4,0xbd0ebd55,0xbd800000,0x3d553d0e,0xbcc4bd6d,0xbc483d7b,0x3d353d35,0xbc48bd7b,0xbcc43d6d,0x3d55bd0e,0xbd80,0xbd0e3d55,0x3d6dbcc4,0xbd7bbc48,
0x3d80,0x3d35bd35,0xbd800000,0x3d353d35,0xbd80,0xbd353d35,0x3d800000,0xbd35bd35,0x3d80,0x3d35bd35,0xbd800000,0x3d353d35,0xbd80,0xbd353d35,0x3d800000,0xbd35bd35,
0x3d80,0x3d35bd35,0xbd800000,0x3d353d35,0xbd80,0xbd353d35,0x3d800000,0xbd35bd35,0x3d80,0x3d35bd35,0xbd800000,0x3d353d35,0xbd80,0xbd353d35,0x3d800000,0xbd35bd35,
0xbd353d35,0x3d7b3c48,0xbcc4bd6d,0xbd0e3d55,0xbd80,0xbd553d0e,0x3d6d3cc4,0xbc48bd7b,0xbd35bd35,0xbc483d7b,0x3d6dbcc4,0xbd55bd0e,0x3d800000,0xbd0ebd55,0xbcc43d6d,0x3d7bbc48,
0x3d35bd35,0xbd7bbc48,0x3cc43d6d,0x3d0ebd55,0x3d80,0x3d55bd0e,0xbd6dbcc4,0x3c483d7b,0x3d353d35,0x3c48bd7b,0xbd6d3cc4,0x3d553d0e,0xbd800000,0x3d0e3d55,0x3cc4bd6d,0xbd7b3c48,
0xbd80,0xbd6d3cc4,0x3d353d35,0x3cc4bd6d,0xbd800000,0x3cc43d6d,0x3d35bd35,0xbd6dbcc4,0x3d80,0x3d6dbcc4,0xbd35bd35,0xbcc43d6d,0x3d800000,0xbcc4bd6d,0xbd353d35,0x3d6d3cc4,
0xbd80,0xbd6d3cc4,0x3d353d35,0x3cc4bd6d,0xbd800000,0x3cc43d6d,0x3d35bd35,0xbd6dbcc4,0x3d80,0x3d6dbcc4,0xbd35bd35,0xbcc43d6d,0x3d800000,0xbcc4bd6d,0xbd353d35,0x3d6d3cc4,
0xbd353d35,0x3d553d0e,0x3cc4bd6d,0xbd7bbc48,0xbd800000,0x3c483d7b,0x3d6dbcc4,0xbd0ebd55,0xbd35bd35,0xbd0e3d55,0x3d6d3cc4,0x3c48bd7b,0xbd80,0xbd7b3c48,0x3cc43d6d,0x3d55bd0e,
0x3d35bd35,0xbd55bd0e,0xbcc43d6d,0x3d7b3c48,0x3d800000,0xbc48bd7b,0xbd6d3cc4,0x3d0e3d55,0x3d353d35,0x3d0ebd55,0xbd6dbcc4,0xbc483d7b,0x3d80,0x3d7bbc48,0xbcc4bd6d,0xbd553d0e,
0xbd800000,0x3d800000,0xbd800000,0x3d800000,0xbd800000,0x3d800000,0xbd800000,0x3d800000,0xbd800000,0x3d800000,0xbd800000,0x3d800000,0xbd800000,0x3d800000,0xbd800000,0x3d800000,
0xbd800000,0x3d800000,0xbd800000,0x3d800000,0xbd800000,0x3d800000,0xbd800000,0x3d800000,0xbd800000,0x3d800000,0xbd800000,0x3d800000,0xbd800000,0x3d800000,0xbd800000,0x3d800000,
0xbd35bd35,0x3d0e3d55,0xbcc4bd6d,0x3c483d7b,0xbd800000,0x3d7b3c48,0xbd6dbcc4,0x3d553d0e,0x3d35bd35,0xbd553d0e,0x3d6dbcc4,0xbd7b3c48,0x8000bd80,0xbc483d7b,0x3cc4bd6d,0xbd0e3d55,
0x3d353d35,0xbd0ebd55,0x3cc43d6d,0xbc48bd7b,0x3d800000,0xbd7bbc48,0x3d6d3cc4,0xbd55bd0e,0xbd353d35,0x3d55bd0e,0xbd6d3cc4,0x3d7bbc48,0x80003d80,0x3c48bd7b,0xbcc43d6d,0x3d0ebd55,
0x3d800000,0xbd6dbcc4,0x3d353d35,0xbcc4bd6d,0x80003d80,0x3cc4bd6d,0xbd353d35,0x3d6dbcc4,0xbd800000,0x3d6d3cc4,0xbd35bd35,0x3cc43d6d,0x8000bd80,0xbcc43d6d,0x3d35bd35,0xbd6d3cc4,
0x3d800000,0xbd6dbcc4,0x3d353d35,0xbcc4bd6d,0x80003d80,0x3cc4bd6d,0xbd353d35,0x3d6dbcc4,0xbd800000,0x3d6d3cc4,0xbd35bd35,0x3cc43d6d,0x8000bd80,0xbcc43d6d,0x3d35bd35,0xbd6d3cc4,
0xbd35bd35,0x3c483d7b,0x3cc4bd6d,0xbd553d0e,0x80003d80,0x3d0ebd55,0xbd6d3cc4,0x3d7b3c48,0x3d35bd35,0xbd7b3c48,0x3d6d3cc4,0xbd0ebd55,0xbd800000,0x3d553d0e,0xbcc4bd6d,0xbc483d7b,
0x3d353d35,0xbc48bd7b,0xbcc43d6d,0x3d55bd0e,0x8000bd80,0xbd0e3d55,0x3d6dbcc4,0xbd7bbc48,0xbd353d35,0x3d7bbc48,0xbd6dbcc4,0x3d0e3d55,0x3d800000,0xbd55bd0e,0x3cc43d6d,0x3c48bd7b,
0xbd800000,0x3d353d35,0x8000bd80,0xbd353d35,0x3d800000,0xbd35bd35,0x80003d80,0x3d35bd35,0xbd800000,0x3d353d35,0x8000bd80,0xbd353d35,0x3d800000,0xbd35bd35,0x80003d80,0x3d35bd35,
0xbd800000,0x3d353d35,0x8000bd80,0xbd353d35,0x3d800000,0xbd35bd35,0x80003d80,0x3d35bd35,0xbd800000,0x3d353d35,0x8000bd80,0xbd353d35,0x3d800000,0xbd35bd35,0x80003d80,0x3d35bd35,
0xbd35bd35,0xbc483d7b,0x3d6dbcc4,0xbd55bd0e,0x3d800000,0xbd0ebd55,0xbcc43d6d,0x3d7bbc48,0x3d35bd35,0xbd7bbc48,0x3cc43d6d,0x3d0ebd55,0x80003d80,0x3d55bd0e,0xbd6dbcc4,0x3c483d7b,
0x3d353d35,0x3c48bd7b,0xbd6d3cc4,0x3d553d0e,0xbd800000,0x3d0e3d55,0x3cc4bd6d,0xbd7b3c48,0xbd353d35,0x3d7b3c48,0xbcc4bd6d,0xbd0e3d55,0x8000bd80,0xbd553d0e,0x3d6d3cc4,0xbc48bd7b,
0x3d800000,0xbcc4bd6d,0xbd353d35,0x3d6d3cc4,0x8000bd80,0xbd6d3cc4,0x3d353d35,0x3cc4bd6d,0xbd800000,0x3cc43d6d,0x3d35bd35,0xbd6dbcc4,0x80003d80,0x3d6dbcc4,0xbd35bd35,0xbcc43d6d,
0x3d800000,0xbcc4bd6d,0xbd353d35,0x3d6d3cc4,0x8000bd80,0xbd6d3cc4,0x3d353d35,0x3cc4bd6d,0xbd800000,0x3cc43d6d,0x3d35bd35,0xbd6dbcc4,0x80003d80,0x3d6dbcc4,0xbd35bd35,0xbcc43d6d,
0xbd35bd35,0xbd0e3d55,0x3d6d3cc4,0x3c48bd7b,0x8000bd80,0xbd7b3c48,0x3cc43d6d,0x3d55bd0e,0x3d35bd35,0xbd55bd0e,0xbcc43d6d,0x3d7b3c48,0x3d800000,0xbc48bd7b,0xbd6d3cc4,0x3d0e3d55,
0x3d353d35,0x3d0ebd55,0xbd6dbcc4,0xbc483d7b,0x80003d80,0x3d7bbc48,0xbcc4bd6d,0xbd553d0e,0xbd353d35,0x3d553d0e,0x3cc4bd6d,0xbd7bbc48,0xbd800000,0x3c483d7b,0x3d6dbcc4,0xbd0ebd55,
0x3d80,0x3d800000,0xbd80,0xbd800000,0x3d80,0x3d800000,0xbd80,0xbd800000,0x3d80,0x3d800000,0xbd80,0xbd800000,0x3d80,0x3d800000,0xbd80,0xbd800000,
0x3d80,0x3d800000,0xbd80,0xbd800000,0x3d80,0x3d800000,0xbd80,0xbd800000,0x3d80,0x3d800000,0xbd80,0xbd800000,0x3d80,0x3d800000,0xbd80,0xbd800000,
0xbd353d35,0x3d0e3d55,0x3d6dbcc4,0xbc48bd7b,0x3d80,0x3d7b3c48,0x3cc4bd6d,0xbd55bd0e,0xbd35bd35,0xbd553d0e,0x3cc43d6d,0x3d7bbc48,0xbd800000,0xbc483d7b,0x3d6d3cc4,0x3d0ebd55,
0x3d35bd35,0xbd0ebd55,0xbd6d3cc4,0x3c483d7b,0xbd80,0xbd7bbc48,0xbcc43d6d,0x3d553d0e,0x3d353d35,0x3d55bd0e,0xbcc4bd6d,0xbd7b3c48,0x3d800000,0x3c48bd7b,0xbd6dbcc4,0xbd0e3d55,
0xbd80,0xbd6dbcc4,0xbd353d35,0x3cc43d6d,0x3d800000,0x3cc4bd6d,0xbd35bd35,0xbd6d3cc4,0x3d80,0x3d6d3cc4,0x3d35bd35,0xbcc4bd6d,0xbd800000,0xbcc43d6d,0x3d353d35,0x3d6dbcc4,
0xbd80,0xbd6dbcc4,0xbd353d35,0x3cc43d6d,0x3d800000,0x3cc4bd6d,0xbd35bd35,0xbd6d3cc4,0x3d80,0x3d6d3cc4,0x3d35bd35,0xbcc4bd6d,0xbd800000,0xbcc43d6d,0x3d353d35,0x3d6dbcc4,
0xbd353d35,0x3c483d7b,0x3d6d3cc4,0x3d55bd0e,0x3d800000,0x3d0ebd55,0xbcc4bd6d,0xbd7bbc48,0xbd35bd35,0xbd7b3c48,0xbcc43d6d,0x3d0e3d55,0x3d80,0x3d553d0e,0x3d6dbcc4,0x3c48bd7b,
0x3d35bd35,0xbc48bd7b,0xbd6dbcc4,0xbd553d0e,0xbd800000,0xbd0e3d55,0x3cc43d6d,0x3d7b3c48,0x3d353d35,0x3d7bbc48,0x3cc4bd6d,0xbd0ebd55,0xbd80,0xbd55bd0e,0xbd6d3cc4,0xbc483d7b,
0x3d80,0x3d353d35,0x3d800000,0x3d35bd35,0xbd80,0xbd35bd35,0xbd800000,0xbd353d35,0x3d80,0x3d353d35,0x3d800000,0x3d35bd35,0xbd80,0xbd35bd35,0xbd800000,0xbd353d35,
0x3d80,0x3d353d35,0x3d800000,0x3d35bd35,0xbd80,0xbd35bd35,0xbd800000,0xbd353d35,0x3d80,0x3d353d35,0x3d800000,0x3d35bd35,0xbd80,0xbd35bd35,0xbd800000,0xbd353d35,
0xbd353d35,0xbc483d7b,0x3cc43d6d,0x3d553d0e,0xbd80,0xbd0ebd55,0xbd6dbcc4,0xbd7b3c48,0xbd35bd35,0xbd7bbc48,0xbd6d3cc4,0xbd0e3d55,0x3d800000,0x3d55bd0e,0x3cc4bd6d,0xbc48bd7b,
0x3d35bd35,0x3c48bd7b,0xbcc4bd6d,0xbd55bd0e,0x3d80,0x3d0e3d55,0x3d6d3cc4,0x3d7bbc48,0x3d353d35,0x3d7b3c48,0x3d6dbcc4,0x3d0ebd55,0xbd800000,0xbd553d0e,0xbcc43d6d,0x3c483d7b,
0xbd80,0xbcc4bd6d,0xbd35bd35,0xbd6dbcc4,0xbd800000,0xbd6d3cc4,0xbd353d35,0xbcc43d6d,0x3d80,0x3cc43d6d,0x3d353d35,0x3d6d3cc4,0x3d800000,0x3d6dbcc4,0x3d35bd35,0x3cc4bd6d,
0xbd80,0xbcc4bd6d,0xbd35bd35,0xbd6dbcc4,0xbd800000,0xbd6d3cc4,0xbd353d35,0xbcc43d6d,0x3d80,0x3cc43d6d,0x3d353d35,0x3d6d3cc4,0x3d800000,0x3d6dbcc4,0x3d35bd35,0x3cc4bd6d,
0xbd353d35,0xbd0e3d55,0xbcc43d6d,0xbc483d7b,0xbd800000,0xbd7b3c48,0xbd6d3cc4,0xbd553d0e,0xbd35bd35,0xbd55bd0e,0xbd6dbcc4,0xbd7bbc48,0xbd80,0xbc48bd7b,0xbcc4bd6d,0xbd0ebd55,
0x3d35bd35,0x3d0ebd55,0x3cc4bd6d,0x3c48bd7b,0x3d800000,0x3d7bbc48,0x3d6dbcc4,0x3d55bd0e,0x3d353d35,0x3d553d0e,0x3d6d3cc4,0x3d7b3c48,0x3d80,0x3c483d7b,0x3cc43d6d,0x3d0e3d55,
0xbd800000,0x80003d80,0x3d800000,0x8000bd80,0xbd800000,0x80003d80,0x3d800000,0x8000bd80,0xbd800000,0x80003d80,0x3d800000,0x8000bd80,0xbd800000,0x80003d80,0x3d800000,0x8000bd80,
0xbd800000,0x80003d80,0x3d800000,0x8000bd80,0xbd800000,0x80003d80,0x3d800000,0x8000bd80,0xbd800000,0x80003d80,0x3d800000,0x8000bd80,0xbd800000,0x80003d80,0x3d800000,0x8000bd80,
0xbd35bd35,0xbd553d0e,0x3cc43d6d,0x3d7bbc48,0xbd800000,0xbc483d7b,0x3d6d3cc4,0x3d0ebd55,0x3d35bd35,0xbd0ebd55,0xbd6d3cc4,0x3c483d7b,0x8000bd80,0xbd7bbc48,0xbcc43d6d,0x3d553d0e,
0x3d353d35,0x3d55bd0e,0xbcc4bd6d,0xbd7b3c48,0x3d800000,0x3c48bd7b,0xbd6dbcc4,0xbd0e3d55,0xbd353d35,0x3d0e3d55,0x3d6dbcc4,0xbc48bd7b,0x80003d80,0x3d7b3c48,0x3cc4bd6d,0xbd55bd0e,
0x3d800000,0x3cc4bd6d,0xbd35bd35,0xbd6d3cc4,0x80003d80,0x3d6d3cc4,0x3d35bd35,0xbcc4bd6d,0xbd800000,0xbcc43d6d,0x3d353d35,0x3d6dbcc4,0x8000bd80,0xbd6dbcc4,0xbd353d35,0x3cc43d6d,
0x3d800000,0x3cc4bd6d,0xbd35bd35,0xbd6d3cc4,0x80003d80,0x3d6d3cc4,0x3d35bd35,0xbcc4bd6d,0xbd800000,0xbcc43d6d,0x3d353d35,0x3d6dbcc4,0x8000bd80,0xbd6dbcc4,0xbd353d35,0x3cc43d6d,
0xbd35bd35,0xbd7b3c48,0xbcc43d6d,0x3d0e3d55,0x80003d80,0x3d553d0e,0x3d6dbcc4,0x3c48bd7b,0x3d35bd35,0xbc48bd7b,0xbd6dbcc4,0xbd553d0e,0xbd800000,0xbd0e3d55,0x3cc43d6d,0x3d7b3c48,
0x3d353d35,0x3d7bbc48,0x3cc4bd6d,0xbd0ebd55,0x8000bd80,0xbd55bd0e,0xbd6d3cc4,0xbc483d7b,0xbd353d35,0x3c483d7b,0x3d6d3cc4,0x3d55bd0e,0x3d800000,0x3d0ebd55,0xbcc4bd6d,0xbd7bbc48,
0xbd800000,0xbd353d35,0x80003d80,0x3d353d35,0x3d800000,0x3d35bd35,0x8000bd80,0xbd35bd35,0xbd800000,0xbd353d35,0x80003d80,0x3d353d35,0x3d800000,0x3d35bd35,0x8000bd80,0xbd35bd35,
0xbd800000,0xbd353d35,0x80003d80,0x3d353d35,0x3d800000,0x3d35bd35,0x8000bd80,0xbd35bd35,0xbd800000,0xbd353d35,0x80003d80,0x3d353d35,0x3d800000,0x3d35bd35,0x8000bd80,0xbd35bd35,
0xbd35bd35,0xbd7bbc48,0xbd6d3cc4,0xbd0e3d55,0x3d800000,0x3d55bd0e,0x3cc4bd6d,0xbc48bd7b,0x3d35bd35,0x3c48bd7b,0xbcc4bd6d,0xbd55bd0e,0x80003d80,0x3d0e3d55,0x3d6d3cc4,0x3d7bbc48,
0x3d353d35,0x3d7b3c48,0x3d6dbcc4,0x3d0ebd55,0xbd800000,0xbd553d0e,0xbcc43d6d,0x3c483d7b,0xbd353d35,0xbc483d7b,0x3cc43d6d,0x3d553d0e,0x8000bd80,0xbd0ebd55,0xbd6dbcc4,0xbd7b3c48,
0x3d800000,0x3d6dbcc4,0x3d35bd35,0x3cc4bd6d,0x8000bd80,0xbcc4bd6d,0xbd35bd35,0xbd6dbcc4,0xbd800000,0xbd6d3cc4,0xbd353d35,0xbcc43d6d,0x80003d80,0x3cc43d6d,0x3d353d35,0x3d6d3cc4,
0x3d800000,0x3d6dbcc4,0x3d35bd35,0x3cc4bd6d,0x8000bd80,0xbcc4bd6d,0xbd35bd35,0xbd6dbcc4,0xbd800000,0xbd6d3cc4,0xbd353d35,0xbcc43d6d,0x80003d80,0x3cc43d6d,0x3d353d35,0x3d6d3cc4,
0xbd35bd35,0xbd55bd0e,0xbd6dbcc4,0xbd7bbc48,0x8000bd80,0xbc48bd7b,0xbcc4bd6d,0xbd0ebd55,0x3d35bd35,0x3d0ebd55,0x3cc4bd6d,0x3c48bd7b,0x3d800000,0x3d7bbc48,0x3d6dbcc4,0x3d55bd0e,
0x3d353d35,0x3d553d0e,0x3d6d3cc4,0x3d7b3c48,0x80003d80,0x3c483d7b,0x3cc43d6d,0x3d0e3d55,0xbd353d35,0xbd0e3d55,0xbcc43d6d,0xbc483d7b,0xbd800000,0xbd7b3c48,0xbd6d3cc4,0xbd553d0e,
0x3d80,0xbb493d80,0xbbc93d7f,0xbc163d7d,0xbc483d7b,0xbc793d78,0xbc953d75,0xbcac3d71,0xbcc43d6d,0xbcdb3d67,0xbcf13d62,0xbd043d5c,0xbd0e3d55,0xbd183d4e,0xbd223d46,0xbd2c3d3e,
0xbd353d35,0xbd3e3d2c,0xbd463d22,0xbd4e3d18,0xbd553d0e,0xbd5c3d04,0xbd623cf1,0xbd673cdb,0xbd6d3cc4,0xbd713cac,0xbd753c95,0xbd783c79,0xbd7b3c48,0xbd7d3c16,0xbd7f3bc9,0xbd803b49,
0xbd553d0e,0xbd713cac,0xbd7f3bc9,0xbd7dbc16,0x3d80,0xbc793d78,0xbcf13d62,0xbd2c3d3e,0xbc48bd7b,0x3b49bd80,0x3c95bd75,0x3d04bd5c,0xbd6dbcc4,0xbd4ebd18,0xbd22bd46,0xbcdbbd67,
0x3d7b3c48,0x3d673cdb,0x3d463d22,0x3d183d4e,0x3d35bd35,0x3d5cbd04,0x3d75bc95,0x3d80bb49,0xbd0e3d55,0xbd3e3d2c,0xbd623cf1,0xbd783c79,0x3cc43d6d,0x3c163d7d,0xbbc93d7f,0xbcac3d71,
0x3cc4bd6d,0x3d3ebd2c,0x3d75bc95,0x3d7d3c16,0x3d553d0e,0x3d043d5c,0x3bc93d7f,0xbcac3d71,0x3d80,0xbcdb3d67,0xbd463d22,0xbd783c79,0xbd7bbc48,0xbd4ebd18,0xbcf1bd62,0xbb49bd80,
0x3d6dbcc4,0x3d803b49,0x3d623cf1,0x3d183d4e,0x3c483d7b,0xbc793d78,0xbd223d46,0xbd673cdb,0xbd353d35,0xbd713cac,0xbd7fbbc9,0xbd5cbd04,0xbd0ebd55,0xbc16bd7d,0x3c95bd75,0x3d2cbd3e,
0xbd7b3c48,0xbd67bcdb,0xbcf1bd62,0x3c16bd7d,0x3d6d3cc4,0x3d043d5c,0xbbc93d7f,0xbd2c3d3e,0xbd0ebd55,0x3b49bd80,0x3d22bd46,0x3d78bc79,0x3d80,0xbd183d4e,0xbd753c95,0xbd71bcac,
0x3d553d0e,0x3cac3d71,0xbc953d75,0xbd4e3d18,0xbcc4bd6d,0x3c79bd78,0x3d46bd22,0x3d80bb49,0xbc483d7b,0xbd3e3d2c,0xbd7f3bc9,0xbd5cbd04,0x3d35bd35,0x3d7dbc16,0x3d623cf1,0x3cdb3d67,
0xbd353d35,0xbd80bb49,0xbd22bd46,0x3c16bd7d,0x3d55bd0e,0x3d783c79,0x3cf13d62,0xbcac3d71,0xbd6d3cc4,0xbd67bcdb,0xbc95bd75,0x3d04bd5c,0x3d7bbc48,0x3d4e3d18,0x3bc93d7f,0xbd2c3d3e,
0x3d80,0xbd3e3d2c,0xbd7fbbc9,0xbd18bd4e,0x3c48bd7b,0x3d5cbd04,0x3d753c95,0x3cdb3d67,0xbcc43d6d,0xbd713cac,0xbd62bcf1,0xbc79bd78,0x3d0ebd55,0x3d7dbc16,0x3d463d22,0x3b493d80,
0xbd7bbc48,0xbcacbd71,0x3d22bd46,0x3d7d3c16,0x3d35bd35,0x3d783c79,0x3c953d75,0xbd2c3d3e,0x3d0ebd55,0x3d803b49,0x3cf13d62,0xbd043d5c,0x3cc43d6d,0xbd183d4e,0xbd7fbbc9,0xbcdbbd67,
0x3d55bd0e,0x3d673cdb,0x3bc93d7f,0xbd4e3d18,0x3d80,0xbd5c3d04,0xbd62bcf1,0xbb49bd80,0x3c483d7b,0xbd3e3d2c,0xbd75bc95,0xbc79bd78,0xbd6dbcc4,0xbc16bd7d,0x3d46bd22,0x3d713cac,
0x3d6dbcc4,0x3d2c3d3e,0xbcf13d62,0xbd7dbc16,0xbc48bd7b,0x3d5cbd04,0x3d463d22,0xbcac3d71,0xbd353d35,0xbd67bcdb,0x3bc9bd7f,0x3d78bc79,0x3d0e3d55,0xbd183d4e,0xbd75bc95,0xbb49bd80,
0x3cc4bd6d,0x3d803b49,0x3c953d75,0xbd4e3d18,0xbd55bd0e,0x3c79bd78,0x3d7fbbc9,0x3cdb3d67,0x3d80,0xbd713cac,0xbd22bd46,0x3d04bd5c,0x3d7b3c48,0x3c163d7d,0xbd623cf1,0xbd3ebd2c,
0xbd55bd0e,0x3cdbbd67,0x3d753c95,0xbc163d7d,0xbcc4bd6d,0x3d5cbd04,0x3d223d46,0xbd2c3d3e,0x3c48bd7b,0x3d803b49,0x3bc93d7f,0xbd783c79,0x3d35bd35,0x3d4e3d18,0xbcf13d62,0xbd71bcac,
0x3d7bbc48,0x3cac3d71,0xbd623cf1,0xbd18bd4e,0x3d6d3cc4,0xbc793d78,0xbd7fbbc9,0xbb49bd80,0x3d0e3d55,0xbd3e3d2c,0xbd46bd22,0x3d04bd5c,0x3d80,0xbd7d3c16,0xbc95bd75,0x3d67bcdb,
0xbd800000,0xbd80bb49,0xbd7fbbc9,0xbd7dbc16,0xbd7bbc48,0xbd78bc79,0xbd75bc95,0xbd71bcac,0xbd6dbcc4,0xbd67bcdb,0xbd62bcf1,0xbd5cbd04,0xbd55bd0e,0xbd4ebd18,0xbd46bd22,0xbd3ebd2c,
0xbd35bd35,0xbd2cbd3e,0xbd22bd46,0xbd18bd4e,0xbd0ebd55,0xbd04bd5c,0xbcf1bd62,0xbcdbbd67,0xbcc4bd6d,0xbcacbd71,0xbc95bd75,0xbc79bd78,0xbc48bd7b,0xbc16bd7d,0xbbc9bd7f,0xbb49bd80,
0xbd0ebd55,0xbcacbd71,0xbbc9bd7f,0x3c16bd7d,0xbd800000,0xbd78bc79,0xbd62bcf1,0xbd3ebd2c,0x3d7bbc48,0x3d803b49,0x3d753c95,0x3d5c3d04,0x3cc4bd6d,0x3d18bd4e,0x3d46bd22,0x3d67bcdb,
0xbc483d7b,0xbcdb3d67,0xbd223d46,0xbd4e3d18,0x3d353d35,0x3d043d5c,0x3c953d75,0x3b493d80,0xbd55bd0e,0xbd2cbd3e,0xbcf1bd62,0xbc79bd78,0xbd6d3cc4,0xbd7d3c16,0xbd7fbbc9,0xbd71bcac,
0x3d6d3cc4,0x3d2c3d3e,0x3c953d75,0xbc163d7d,0xbd0e3d55,0xbd5c3d04,0xbd7f3bc9,0xbd71bcac,0xbd800000,0xbd67bcdb,0xbd22bd46,0xbc79bd78,0x3c48bd7b,0x3d18bd4e,0x3d62bcf1,0x3d80bb49,
0x3cc43d6d,0xbb493d80,0xbcf13d62,0xbd4e3d18,0xbd7b3c48,0xbd78bc79,0xbd46bd22,0xbcdbbd67,0xbd35bd35,0xbcacbd71,0x3bc9bd7f,0x3d04bd5c,0x3d55bd0e,0x3d7dbc16,0x3d753c95,0x3d3e3d2c,
0xbc48bd7b,0x3cdbbd67,0x3d62bcf1,0x3d7d3c16,0xbcc43d6d,0xbd5c3d04,0xbd7fbbc9,0xbd3ebd2c,0x3d55bd0e,0x3d803b49,0x3d463d22,0x3c793d78,0xbd800000,0xbd4ebd18,0xbc95bd75,0x3cacbd71,
0xbd0e3d55,0xbd713cac,0xbd75bc95,0xbd18bd4e,0x3d6dbcc4,0x3d783c79,0x3d223d46,0x3b493d80,0xbd7bbc48,0xbd2cbd3e,0xbbc9bd7f,0x3d04bd5c,0x3d353d35,0x3c163d7d,0xbcf13d62,0xbd673cdb,
0xbd35bd35,0x3b49bd80,0x3d46bd22,0x3d7d3c16,0x3d0e3d55,0xbc793d78,0xbd623cf1,0xbd71bcac,0xbcc4bd6d,0x3cdbbd67,0x3d75bc95,0x3d5c3d04,0x3c483d7b,0xbd183d4e,0xbd7f3bc9,0xbd3ebd2c,
0xbd800000,0xbd2cbd3e,0x3bc9bd7f,0x3d4ebd18,0x3d7b3c48,0x3d043d5c,0xbc953d75,0xbd673cdb,0xbd6dbcc4,0xbcacbd71,0x3cf1bd62,0x3d78bc79,0x3d553d0e,0x3c163d7d,0xbd223d46,0xbd803b49,
0x3c48bd7b,0x3d71bcac,0x3d463d22,0xbc163d7d,0x3d353d35,0xbc793d78,0xbd753c95,0xbd3ebd2c,0x3d553d0e,0xbb493d80,0xbd623cf1,0xbd5cbd04,0xbd6d3cc4,0xbd4ebd18,0x3bc9bd7f,0x3d67bcdb,
0x3d0e3d55,0xbcdb3d67,0xbd7f3bc9,0xbd18bd4e,0xbd800000,0xbd04bd5c,0x3cf1bd62,0x3d80bb49,0xbd7b3c48,0xbd2cbd3e,0x3c95bd75,0x3d78bc79,0x3cc4bd6d,0x3d7dbc16,0x3d223d46,0xbcac3d71,
0x3cc43d6d,0xbd3e3d2c,0xbd62bcf1,0x3c16bd7d,0x3d7bbc48,0x3d043d5c,0xbd223d46,0xbd71bcac,0xbd35bd35,0x3cdbbd67,0x3d7f3bc9,0x3c793d78,0xbd553d0e,0xbd4ebd18,0x3c95bd75,0x3d80bb49,
0x3d6d3cc4,0xbb493d80,0xbd753c95,0xbd18bd4e,0x3d0ebd55,0x3d783c79,0x3bc93d7f,0xbd673cdb,0xbd800000,0xbcacbd71,0x3d46bd22,0x3d5c3d04,0xbc483d7b,0xbd7d3c16,0xbcf1bd62,0x3d2cbd3e,
0x3d0ebd55,0x3d673cdb,0xbc953d75,0xbd7dbc16,0x3d6dbcc4,0x3d043d5c,0xbd463d22,0xbd3ebd2c,0x3d7b3c48,0xbb493d80,0xbd7f3bc9,0xbc79bd78,0x3d353d35,0xbd183d4e,0xbd62bcf1,0x3cacbd71,
0x3c483d7b,0xbd713cac,0xbcf1bd62,0x3d4ebd18,0xbcc43d6d,0xbd78bc79,0x3bc9bd7f,0x3d80bb49,0xbd553d0e,0xbd2cbd3e,0x3d22bd46,0x3d5c3d04,0xbd800000,0xbc16bd7d,0x3d75bc95,0x3cdb3d67,
0x3d80,0xbd80bb49,0x3bc9bd7f,0x3d7d3c16,0xbc483d7b,0xbd78bc79,0x3c95bd75,0x3d713cac,0xbcc43d6d,0xbd67bcdb,0x3cf1bd62,0x3d5c3d04,0xbd0e3d55,0xbd4ebd18,0x3d22bd46,0x3d3e3d2c,
0xbd353d35,0xbd2cbd3e,0x3d46bd22,0x3d183d4e,0xbd553d0e,0xbd04bd5c,0x3d62bcf1,0x3cdb3d67,0xbd6d3cc4,0xbcacbd71,0x3d75bc95,0x3c793d78,0xbd7b3c48,0xbc16bd7d,0x3d7fbbc9,0x3b493d80,
0xbd553d0e,0xbcacbd71,0x3d7fbbc9,0xbc163d7d,0x3d80,0xbd78bc79,0x3cf1bd62,0x3d3e3d2c,0xbc48bd7b,0x3d803b49,0xbc953d75,0xbd5cbd04,0xbd6dbcc4,0x3d18bd4e,0x3d223d46,0xbd673cdb,
0x3d7b3c48,0xbcdb3d67,0xbd46bd22,0x3d4ebd18,0x3d35bd35,0x3d043d5c,0xbd753c95,0xbb49bd80,0xbd0e3d55,0xbd2cbd3e,0x3d62bcf1,0x3c793d78,0x3cc43d6d,0xbd7d3c16,0x3bc9bd7f,0x3d713cac,
0x3cc4bd6d,0x3d2c3d3e,0xbd753c95,0x3c16bd7d,0x3d553d0e,0xbd5c3d04,0xbbc9bd7f,0x3d713cac,0x3d80,0xbd67bcdb,0x3d46bd22,0x3c793d78,0xbd7bbc48,0x3d18bd4e,0x3cf13d62,0xbd803b49,
0x3d6dbcc4,0xbb493d80,0xbd62bcf1,0x3d4ebd18,0x3c483d7b,0xbd78bc79,0x3d22bd46,0x3cdb3d67,0xbd353d35,0xbcacbd71,0x3d7f3bc9,0xbd043d5c,0xbd0ebd55,0x3d7dbc16,0xbc953d75,0xbd3ebd2c,
0xbd7b3c48,0x3cdbbd67,0x3cf13d62,0xbd7dbc16,0x3d6d3cc4,0xbd5c3d04,0x3bc9bd7f,0x3d3e3d2c,0xbd0ebd55,0x3d803b49,0xbd223d46,0xbc79bd78,0x3d80,0xbd4ebd18,0x3d75bc95,0xbcac3d71,
0x3d553d0e,0xbd713cac,0x3c95bd75,0x3d183d4e,0xbcc4bd6d,0x3d783c79,0xbd463d22,0xbb49bd80,0xbc483d7b,0xbd2cbd3e,0x3d7fbbc9,0xbd043d5c,0x3d35bd35,0x3c163d7d,0xbd62bcf1,0x3d67bcdb,
0xbd353d35,0x3b49bd80,0x3d223d46,0xbd7dbc16,0x3d55bd0e,0xbc793d78,0xbcf1bd62,0x3d713cac,0xbd6d3cc4,0x3cdbbd67,0x3c953d75,0xbd5cbd04,0x3d7bbc48,0xbd183d4e,0xbbc9bd7f,0x3d3e3d2c,
0x3d80,0xbd2cbd3e,0x3d7f3bc9,0xbd4e3d18,0x3c48bd7b,0x3d043d5c,0xbd75bc95,0x3d67bcdb,0xbcc43d6d,0xbcacbd71,0x3d623cf1,0xbd783c79,0x3d0ebd55,0x3c163d7d,0xbd46bd22,0x3d80bb49,
0xbd7bbc48,0x3d71bcac,0xbd223d46,0x3c16bd7d,0x3d35bd35,0xbc793d78,0xbc95bd75,0x3d3e3d2c,0x3d0ebd55,0xbb493d80,0xbcf1bd62,0x3d5c3d04,0x3cc43d6d,0xbd4ebd18,0x3d7f3bc9,0xbd673cdb,
0x3d55bd0e,0xbcdb3d67,0xbbc9bd7f,0x3d183d4e,0x3d80,0xbd04bd5c,0x3d623cf1,0xbd803b49,0x3c483d7b,0xbd2cbd3e,0x3d753c95,0xbd783c79,0xbd6dbcc4,0x3d7dbc16,0xbd463d22,0x3cacbd71,
0x3d6dbcc4,0xbd3e3d2c,0x3cf1bd62,0xbc163d7d,0xbc48bd7b,0x3d043d5c,0xbd46bd22,0x3d713cac,0xbd353d35,0x3cdbbd67,0xbbc93d7f,0xbc79bd78,0x3d0e3d55,0xbd4ebd18,0x3d753c95,0xbd803b49,
0x3cc4bd6d,0xbb493d80,0xbc95bd75,0x3d183d4e,0xbd55bd0e,0x3d783c79,0xbd7f3bc9,0x3d67bcdb,0x3d80,0xbcacbd71,0x3d223d46,0xbd5cbd04,0x3d7b3c48,0xbd7d3c16,0x3d62bcf1,0xbd2c3d3e,
0xbd55bd0e,0x3d673cdb,0xbd75bc95,0x3d7d3c16,0xbcc4bd6d,0x3d043d5c,0xbd22bd46,0x3d3e3d2c,0x3c48bd7b,0xbb493d80,0xbbc9bd7f,0x3c793d78,0x3d35bd35,0xbd183d4e,0x3cf1bd62,0xbcac3d71,
0x3d7bbc48,0xbd713cac,0x3d62bcf1,0xbd4e3d18,0x3d6d3cc4,0xbd78bc79,0x3d7f3bc9,0xbd803b49,0x3d0e3d55,0xbd2cbd3e,0x3d463d22,0xbd5cbd04,0x3d80,0xbc16bd7d,0x3c953d75,0xbcdbbd67,
0xbd800000,0x3b49bd80,0x3d7f3bc9,0xbc163d7d,0xbd7bbc48,0x3c79bd78,0x3d753c95,0xbcac3d71,0xbd6dbcc4,0x3cdbbd67,0x3d623cf1,0xbd043d5c,0xbd55bd0e,0x3d18bd4e,0x3d463d22,0xbd2c3d3e,
0xbd35bd35,0x3d3ebd2c,0x3d223d46,0xbd4e3d18,0xbd0ebd55,0x3d5cbd04,0x3cf13d62,0xbd673cdb,0xbcc4bd6d,0x3d71bcac,0x3c953d75,0xbd783c79,0xbc48bd7b,0x3d7dbc16,0x3bc93d7f,0xbd803b49,
0xbd0ebd55,0x3d71bcac,0x3bc93d7f,0xbd7dbc16,0xbd800000,0x3c79bd78,0x3d623cf1,0xbd2c3d3e,0x3d7bbc48,0xbb493d80,0xbd75bc95,0x3d04bd5c,0x3cc4bd6d,0x3d4e3d18,0xbd463d22,0xbcdbbd67,
0xbc483d7b,0xbd67bcdb,0x3d22bd46,0x3d183d4e,0x3d353d35,0xbd5c3d04,0xbc95bd75,0x3d80bb49,0xbd55bd0e,0x3d3ebd2c,0x3cf13d62,0xbd783c79,0xbd6d3cc4,0xbc16bd7d,0x3d7f3bc9,0xbcac3d71,
0x3d6d3cc4,0xbd3e3d2c,0xbc95bd75,0x3d7d3c16,0xbd0e3d55,0xbd04bd5c,0x3d7fbbc9,0xbcac3d71,0xbd800000,0x3cdbbd67,0x3d223d46,0xbd783c79,0x3c48bd7b,0x3d4e3d18,0xbd623cf1,0xbb49bd80,
0x3cc43d6d,0xbd80bb49,0x3cf1bd62,0x3d183d4e,0xbd7b3c48,0x3c79bd78,0x3d463d22,0xbd673cdb,0xbd35bd35,0x3d71bcac,0xbbc93d7f,0xbd5cbd04,0x3d55bd0e,0x3c163d7d,0xbd75bc95,0x3d2cbd3e,
0xbc48bd7b,0x3d673cdb,0xbd623cf1,0x3c16bd7d,0xbcc43d6d,0xbd04bd5c,0x3d7f3bc9,0xbd2c3d3e,0x3d55bd0e,0xbb493d80,0xbd46bd22,0x3d78bc79,0xbd800000,0x3d18bd4e,0x3c953d75,0xbd71bcac,
0xbd0e3d55,0xbcacbd71,0x3d753c95,0xbd4e3d18,0x3d6dbcc4,0xbc793d78,0xbd22bd46,0x3d80bb49,0xbd7bbc48,0x3d3ebd2c,0x3bc93d7f,0xbd5cbd04,0x3d353d35,0xbd7d3c16,0x3cf1bd62,0x3cdb3d67,
0xbd35bd35,0x3d803b49,0xbd463d22,0x3c16bd7d,0x3d0e3d55,0xbd78bc79,0x3d62bcf1,0xbcac3d71,0xbcc4bd6d,0x3d673cdb,0xbd753c95,0x3d04bd5c,0x3c483d7b,0xbd4ebd18,0x3d7fbbc9,0xbd2c3d3e,
0xbd800000,0x3d3ebd2c,0xbbc93d7f,0xbd18bd4e,0x3d7b3c48,0xbd5c3d04,0x3c95bd75,0x3cdb3d67,0xbd6dbcc4,0x3d71bcac,0xbcf13d62,0xbc79bd78,0x3d553d0e,0xbd7d3c16,0x3d22bd46,0x3b493d80,
0x3c48bd7b,0x3cac3d71,0xbd46bd22,0x3d7d3c16,0x3d353d35,0xbd78bc79,0x3d75bc95,0xbd2c3d3e,0x3d553d0e,0xbd80bb49,0x3d62bcf1,0xbd043d5c,0xbd6d3cc4,0x3d18bd4e,0xbbc93d7f,0xbcdbbd67,
0x3d0e3d55,0xbd67bcdb,0x3d7fbbc9,0xbd4e3d18,0xbd800000,0x3d5cbd04,0xbcf13d62,0xbb49bd80,0xbd7b3c48,0x3d3ebd2c,0xbc953d75,0xbc79bd78,0x3cc4bd6d,0x3c163d7d,0xbd22bd46,0x3d713cac,
0x3cc43d6d,0xbd2cbd3e,0x3d623cf1,0xbd7dbc16,0x3d7bbc48,0xbd5c3d04,0x3d22bd46,0xbcac3d71,0xbd35bd35,0x3d673cdb,0xbd7fbbc9,0x3d78bc79,0xbd553d0e,0x3d18bd4e,0xbc953d75,0xbb49bd80,
0x3d6d3cc4,0xbd80bb49,0x3d75bc95,0xbd4e3d18,0x3d0ebd55,0xbc793d78,0xbbc9bd7f,0x3cdb3d67,0xbd800000,0x3d71bcac,0xbd463d22,0x3d04bd5c,0xbc483d7b,0xbc16bd7d,0x3cf13d62,0xbd3ebd2c,
0x3d0ebd55,0xbcdb3d67,0x3c95bd75,0xbc163d7d,0x3d6dbcc4,0xbd5c3d04,0x3d46bd22,0xbd2c3d3e,0x3d7b3c48,0xbd80bb49,0x3d7fbbc9,0xbd783c79,0x3d353d35,0xbd4ebd18,0x3d623cf1,0xbd71bcac,
0x3c483d7b,0xbcacbd71,0x3cf13d62,0xbd18bd4e,0xbcc43d6d,0x3c79bd78,0xbbc93d7f,0xbb49bd80,0xbd553d0e,0x3d3ebd2c,0xbd223d46,0x3d04bd5c,0xbd800000,0x3d7dbc16,0xbd753c95,0x3d67bcdb,
0x3d80,0x3b49bd80,0xbbc93d7f,0x3c16bd7d,0xbc483d7b,0x3c79bd78,0xbc953d75,0x3cacbd71,0xbcc43d6d,0x3cdbbd67,0xbcf13d62,0x3d04bd5c,0xbd0e3d55,0x3d18bd4e,0xbd223d46,0x3d2cbd3e,
0xbd353d35,0x3d3ebd2c,0xbd463d22,0x3d4ebd18,0xbd553d0e,0x3d5cbd04,0xbd623cf1,0x3d67bcdb,0xbd6d3cc4,0x3d71bcac,0xbd753c95,0x3d78bc79,0xbd7b3c48,0x3d7dbc16,0xbd7f3bc9,0x3d80bb49,
0xbd553d0e,0x3d71bcac,0xbd7f3bc9,0x3d7d3c16,0x3d80,0x3c79bd78,0xbcf13d62,0x3d2cbd3e,0xbc48bd7b,0xbb493d80,0x3c95bd75,0xbd043d5c,0xbd6dbcc4,0x3d4e3d18,0xbd22bd46,0x3cdb3d67,
0x3d7b3c48,0xbd67bcdb,0x3d463d22,0xbd18bd4e,0x3d35bd35,0xbd5c3d04,0x3d75bc95,0xbd803b49,0xbd0e3d55,0x3d3ebd2c,0xbd623cf1,0x3d78bc79,0x3cc43d6d,0xbc16bd7d,0xbbc93d7f,0x3cacbd71,
0x3cc4bd6d,0xbd3e3d2c,0x3d75bc95,0xbd7dbc16,0x3d553d0e,0xbd04bd5c,0x3bc93d7f,0x3cacbd71,0x3d80,0x3cdbbd67,0xbd463d22,0x3d78bc79,0xbd7bbc48,0x3d4e3d18,0xbcf1bd62,0x3b493d80,
0x3d6dbcc4,0xbd80bb49,0x3d623cf1,0xbd18bd4e,0x3c483d7b,0x3c79bd78,0xbd223d46,0x3d67bcdb,0xbd353d35,0x3d71bcac,0xbd7fbbc9,0x3d5c3d04,0xbd0ebd55,0x3c163d7d,0x3c95bd75,0xbd2c3d3e,
0xbd7b3c48,0x3d673cdb,0xbcf1bd62,0xbc163d7d,0x3d6d3cc4,0xbd04bd5c,0xbbc93d7f,0x3d2cbd3e,0xbd0ebd55,0xbb493d80,0x3d22bd46,0xbd783c79,0x3d80,0x3d18bd4e,0xbd753c95,0x3d713cac,
0x3d553d0e,0xbcacbd71,0xbc953d75,0x3d4ebd18,0xbcc4bd6d,0xbc793d78,0x3d46bd22,0xbd803b49,0xbc483d7b,0x3d3ebd2c,0xbd7f3bc9,0x3d5c3d04,0x3d35bd35,0xbd7d3c16,0x3d623cf1,0xbcdbbd67,
0xbd353d35,0x3d803b49,0xbd22bd46,0xbc163d7d,0x3d55bd0e,0xbd78bc79,0x3cf13d62,0x3cacbd71,0xbd6d3cc4,0x3d673cdb,0xbc95bd75,0xbd043d5c,0x3d7bbc48,0xbd4ebd18,0x3bc93d7f,0x3d2cbd3e,
0x3d80,0x3d3ebd2c,0xbd7fbbc9,0x3d183d4e,0x3c48bd7b,0xbd5c3d04,0x3d753c95,0xbcdbbd67,0xbcc43d6d,0x3d71bcac,0xbd62bcf1,0x3c793d78,0x3d0ebd55,0xbd7d3c16,0x3d463d22,0xbb49bd80,
0xbd7bbc48,0x3cac3d71,0x3d22bd46,0xbd7dbc16,0x3d35bd35,0xbd78bc79,0x3c953d75,0x3d2cbd3e,0x3d0ebd55,0xbd80bb49,0x3cf13d62,0x3d04bd5c,0x3cc43d6d,0x3d18bd4e,0xbd7fbbc9,0x3cdb3d67,
0x3d55bd0e,0xbd67bcdb,0x3bc93d7f,0x3d4ebd18,0x3d80,0x3d5cbd04,0xbd62bcf1,0x3b493d80,0x3c483d7b,0x3d3ebd2c,0xbd75bc95,0x3c793d78,0xbd6dbcc4,0x3c163d7d,0x3d46bd22,0xbd71bcac,
0x3d6dbcc4,0xbd2cbd3e,0xbcf13d62,0x3d7d3c16,0xbc48bd7b,0xbd5c3d04,0x3d463d22,0x3cacbd71,0xbd353d35,0x3d673cdb,0x3bc9bd7f,0xbd783c79,0x3d0e3d55,0x3d18bd4e,0xbd75bc95,0x3b493d80,
0x3cc4bd6d,0xbd80bb49,0x3c953d75,0x3d4ebd18,0xbd55bd0e,0xbc793d78,0x3d7fbbc9,0xbcdbbd67,0x3d80,0x3d71bcac,0xbd22bd46,0xbd043d5c,0x3d7b3c48,0xbc16bd7d,0xbd623cf1,0x3d3e3d2c,
0xbd55bd0e,0xbcdb3d67,0x3d753c95,0x3c16bd7d,0xbcc4bd6d,0xbd5c3d04,0x3d223d46,0x3d2cbd3e,0x3c48bd7b,0xbd80bb49,0x3bc93d7f,0x3d78bc79,0x3d35bd35,0xbd4ebd18,0xbcf13d62,0x3d713cac,
0x3d7bbc48,0xbcacbd71,0xbd623cf1,0x3d183d4e,0x3d6d3cc4,0x3c79bd78,0xbd7fbbc9,0x3b493d80,0x3d0e3d55,0x3d3ebd2c,0xbd46bd22,0xbd043d5c,0x3d80,0x3d7dbc16,0xbc95bd75,0xbd673cdb,
0xbd800000,0x3d803b49,0xbd7fbbc9,0x3d7d3c16,0xbd7bbc48,0x3d783c79,0xbd75bc95,0x3d713cac,0xbd6dbcc4,0x3d673cdb,0xbd62bcf1,0x3d5c3d04,0xbd55bd0e,0x3d4e3d18,0xbd46bd22,0x3d3e3d2c,
0xbd35bd35,0x3d2c3d3e,0xbd22bd46,0x3d183d4e,0xbd0ebd55,0x3d043d5c,0xbcf1bd62,0x3cdb3d67,0xbcc4bd6d,0x3cac3d71,0xbc95bd75,0x3c793d78,0xbc48bd7b,0x3c163d7d,0xbbc9bd7f,0x3b493d80,
0xbd0ebd55,0x3cac3d71,0xbbc9bd7f,0xbc163d7d,0xbd800000,0x3d783c79,0xbd62bcf1,0x3d3e3d2c,0x3d7bbc48,0xbd80bb49,0x3d753c95,0xbd5cbd04,0x3cc4bd6d,0xbd183d4e,0x3d46bd22,0xbd673cdb,
0xbc483d7b,0x3cdbbd67,0xbd223d46,0x3d4ebd18,0x3d353d35,0xbd04bd5c,0x3c953d75,0xbb49bd80,0xbd55bd0e,0x3d2c3d3e,0xbcf1bd62,0x3c793d78,0xbd6d3cc4,0x3d7dbc16,0xbd7fbbc9,0x3d713cac,
0x3d6d3cc4,0xbd2cbd3e,0x3c953d75,0x3c16bd7d,0xbd0e3d55,0x3d5cbd04,0xbd7f3bc9,0x3d713cac,0xbd800000,0x3d673cdb,0xbd22bd46,0x3c793d78,0x3c48bd7b,0xbd183d4e,0x3d62bcf1,0xbd803b49,
0x3cc43d6d,0x3b49bd80,0xbcf13d62,0x3d4ebd18,0xbd7b3c48,0x3d783c79,0xbd46bd22,0x3cdb3d67,0xbd35bd35,0x3cac3d71,0x3bc9bd7f,0xbd043d5c,0x3d55bd0e,0xbd7d3c16,0x3d753c95,0xbd3ebd2c,
0xbc48bd7b,0xbcdb3d67,0x3d62bcf1,0xbd7dbc16,0xbcc43d6d,0x3d5cbd04,0xbd7fbbc9,0x3d3e3d2c,0x3d55bd0e,0xbd80bb49,0x3d463d22,0xbc79bd78,0xbd800000,0x3d4e3d18,0xbc95bd75,0xbcac3d71,
0xbd0e3d55,0x3d71bcac,0xbd75bc95,0x3d183d4e,0x3d6dbcc4,0xbd78bc79,0x3d223d46,0xbb49bd80,0xbd7bbc48,0x3d2c3d3e,0xbbc9bd7f,0xbd043d5c,0x3d353d35,0xbc16bd7d,0xbcf13d62,0x3d67bcdb,
0xbd35bd35,0xbb493d80,0x3d46bd22,0xbd7dbc16,0x3d0e3d55,0x3c79bd78,0xbd623cf1,0x3d713cac,0xbcc4bd6d,0xbcdb3d67,0x3d75bc95,0xbd5cbd04,0x3c483d7b,0x3d18bd4e,0xbd7f3bc9,0x3d3e3d2c,
0xbd800000,0x3d2c3d3e,0x3bc9bd7f,0xbd4e3d18,0x3d7b3c48,0xbd04bd5c,0xbc953d75,0x3d67bcdb,0xbd6dbcc4,0x3cac3d71,0x3cf1bd62,0xbd783c79,0x3d553d0e,0xbc16bd7d,0xbd223d46,0x3d80bb49,
0x3c48bd7b,0xbd713cac,0x3d463d22,0x3c16bd7d,0x3d353d35,0x3c79bd78,0xbd753c95,0x3d3e3d2c,0x3d553d0e,0x3b49bd80,0xbd623cf1,0x3d5c3d04,0xbd6d3cc4,0x3d4e3d18,0x3bc9bd7f,0xbd673cdb,
0x3d0e3d55,0x3cdbbd67,0xbd7f3bc9,0x3d183d4e,0xbd800000,0x3d043d5c,0x3cf1bd62,0xbd803b49,0xbd7b3c48,0x3d2c3d3e,0x3c95bd75,0xbd783c79,0x3cc4bd6d,0xbd7d3c16,0x3d223d46,0x3cacbd71,
0x3cc43d6d,0x3d3ebd2c,0xbd62bcf1,0xbc163d7d,0x3d7bbc48,0xbd04bd5c,0xbd223d46,0x3d713cac,0xbd35bd35,0xbcdb3d67,0x3d7f3bc9,0xbc79bd78,0xbd553d0e,0x3d4e3d18,0x3c95bd75,0xbd803b49,
0x3d6d3cc4,0x3b49bd80,0xbd753c95,0x3d183d4e,0x3d0ebd55,0xbd78bc79,0x3bc93d7f,0x3d67bcdb,0xbd800000,0x3cac3d71,0x3d46bd22,0xbd5cbd04,0xbc483d7b,0x3d7dbc16,0xbcf1bd62,0xbd2c3d3e,
0x3d0ebd55,0xbd67bcdb,0xbc953d75,0x3d7d3c16,0x3d6dbcc4,0xbd04bd5c,0xbd463d22,0x3d3e3d2c,0x3d7b3c48,0x3b49bd80,0xbd7f3bc9,0x3c793d78,0x3d353d35,0x3d18bd4e,0xbd62bcf1,0xbcac3d71,
0x3c483d7b,0x3d71bcac,0xbcf1bd62,0xbd4e3d18,0xbcc43d6d,0x3d783c79,0x3bc9bd7f,0xbd803b49,0xbd553d0e,0x3d2c3d3e,0x3d22bd46,0xbd5cbd04,0xbd800000,0x3c163d7d,0x3d75bc95,0xbcdbbd67,
0x3d80,0x3d803b49,0x3bc9bd7f,0xbd7dbc16,0xbc483d7b,0x3d783c79,0x3c95bd75,0xbd71bcac,0xbcc43d6d,0x3d673cdb,0x3cf1bd62,0xbd5cbd04,0xbd0e3d55,0x3d4e3d18,0x3d22bd46,0xbd3ebd2c,
0xbd353d35,0x3d2c3d3e,0x3d46bd22,0xbd18bd4e,0xbd553d0e,0x3d043d5c,0x3d62bcf1,0xbcdbbd67,0xbd6d3cc4,0x3cac3d71,0x3d75bc95,0xbc79bd78,0xbd7b3c48,0x3c163d7d,0x3d7fbbc9,0xbb49bd80,
0xbd553d0e,0x3cac3d71,0x3d7fbbc9,0x3c16bd7d,0x3d80,0x3d783c79,0x3cf1bd62,0xbd3ebd2c,0xbc48bd7b,0xbd80bb49,0xbc953d75,0x3d5c3d04,0xbd6dbcc4,0xbd183d4e,0x3d223d46,0x3d67bcdb,
0x3d7b3c48,0x3cdbbd67,0xbd46bd22,0xbd4e3d18,0x3d35bd35,0xbd04bd5c,0xbd753c95,0x3b493d80,0xbd0e3d55,0x3d2c3d3e,0x3d62bcf1,0xbc79bd78,0x3cc43d6d,0x3d7dbc16,0x3bc9bd7f,0xbd71bcac,
0x3cc4bd6d,0xbd2cbd3e,0xbd753c95,0xbc163d7d,0x3d553d0e,0x3d5cbd04,0xbbc9bd7f,0xbd71bcac,0x3d80,0x3d673cdb,0x3d46bd22,0xbc79bd78,0xbd7bbc48,0xbd183d4e,0x3cf13d62,0x3d80bb49,
0x3d6dbcc4,0x3b49bd80,0xbd62bcf1,0xbd4e3d18,0x3c483d7b,0x3d783c79,0x3d22bd46,0xbcdbbd67,0xbd353d35,0x3cac3d71,0x3d7f3bc9,0x3d04bd5c,0xbd0ebd55,0xbd7d3c16,0xbc953d75,0x3d3e3d2c,
0xbd7b3c48,0xbcdb3d67,0x3cf13d62,0x3d7d3c16,0x3d6d3cc4,0x3d5cbd04,0x3bc9bd7f,0xbd3ebd2c,0xbd0ebd55,0xbd80bb49,0xbd223d46,0x3c793d78,0x3d80,0x3d4e3d18,0x3d75bc95,0x3cacbd71,
0x3d553d0e,0x3d71bcac,0x3c95bd75,0xbd18bd4e,0xbcc4bd6d,0xbd78bc79,0xbd463d22,0x3b493d80,0xbc483d7b,0x3d2c3d3e,0x3d7fbbc9,0x3d04bd5c,0x3d35bd35,0xbc16bd7d,0xbd62bcf1,0xbd673cdb,
0xbd353d35,0xbb493d80,0x3d223d46,0x3d7d3c16,0x3d55bd0e,0x3c79bd78,0xbcf1bd62,0xbd71bcac,0xbd6d3cc4,0xbcdb3d67,0x3c953d75,0x3d5c3d04,0x3d7bbc48,0x3d18bd4e,0xbbc9bd7f,0xbd3ebd2c,
0x3d80,0x3d2c3d3e,0x3d7f3bc9,0x3d4ebd18,0x3c48bd7b,0xbd04bd5c,0xbd75bc95,0xbd673cdb,0xbcc43d6d,0x3cac3d71,0x3d623cf1,0x3d78bc79,0x3d0ebd55,0xbc16bd7d,0xbd46bd22,0xbd803b49,
0xbd7bbc48,0xbd713cac,0xbd223d46,0xbc163d7d,0x3d35bd35,0x3c79bd78,0xbc95bd75,0xbd3ebd2c,0x3d0ebd55,0x3b49bd80,0xbcf1bd62,0xbd5cbd04,0x3cc43d6d,0x3d4e3d18,0x3d7f3bc9,0x3d67bcdb,
0x3d55bd0e,0x3cdbbd67,0xbbc9bd7f,0xbd18bd4e,0x3d80,0x3d043d5c,0x3d623cf1,0x3d80bb49,0x3c483d7b,0x3d2c3d3e,0x3d753c95,0x3d78bc79,0xbd6dbcc4,0xbd7d3c16,0xbd463d22,0xbcac3d71,
0x3d6dbcc4,0x3d3ebd2c,0x3cf1bd62,0x3c16bd7d,0xbc48bd7b,0xbd04bd5c,0xbd46bd22,0xbd71bcac,0xbd353d35,0xbcdb3d67,0xbbc93d7f,0x3c793d78,0x3d0e3d55,0x3d4e3d18,0x3d753c95,0x3d80bb49,
0x3cc4bd6d,0x3b49bd80,0xbc95bd75,0xbd18bd4e,0xbd55bd0e,0xbd78bc79,0xbd7f3bc9,0xbd673cdb,0x3d80,0x3cac3d71,0x3d223d46,0x3d5c3d04,0x3d7b3c48,0x3d7dbc16,0x3d62bcf1,0x3d2cbd3e,
0xbd55bd0e,0xbd67bcdb,0xbd75bc95,0xbd7dbc16,0xbcc4bd6d,0xbd04bd5c,0xbd22bd46,0xbd3ebd2c,0x3c48bd7b,0x3b49bd80,0xbbc9bd7f,0xbc79bd78,0x3d35bd35,0x3d18bd4e,0x3cf1bd62,0x3cacbd71,
0x3d7bbc48,0x3d71bcac,0x3d62bcf1,0x3d4ebd18,0x3d6d3cc4,0x3d783c79,0x3d7f3bc9,0x3d80bb49,0x3d0e3d55,0x3d2c3d3e,0x3d463d22,0x3d5c3d04,0x3d80,0x3c163d7d,0x3c953d75,0x3cdb3d67,
0xbd800000,0xbb493d80,0x3d7f3bc9,0x3c16bd7d,0xbd7bbc48,0xbc793d78,0x3d753c95,0x3cacbd71,0xbd6dbcc4,0xbcdb3d67,0x3d623cf1,0x3d04bd5c,0xbd55bd0e,0xbd183d4e,0x3d463d22,0x3d2cbd3e,
0xbd35bd35,0xbd3e3d2c,0x3d223d46,0x3d4ebd18,0xbd0ebd55,0xbd5c3d04,0x3cf13d62,0x3d67bcdb,0xbcc4bd6d,0xbd713cac,0x3c953d75,0x3d78bc79,0xbc48bd7b,0xbd7d3c16,0x3bc93d7f,0x3d80bb49,
0xbd0ebd55,0xbd713cac,0x3bc93d7f,0x3d7d3c16,0xbd800000,0xbc793d78,0x3d623cf1,0x3d2cbd3e,0x3d7bbc48,0x3b49bd80,0xbd75bc95,0xbd043d5c,0x3cc4bd6d,0xbd4ebd18,0xbd463d22,0x3cdb3d67,
0xbc483d7b,0x3d673cdb,0x3d22bd46,0xbd18bd4e,0x3d353d35,0x3d5cbd04,0xbc95bd75,0xbd803b49,0xbd55bd0e,0xbd3e3d2c,0x3cf13d62,0x3d78bc79,0xbd6d3cc4,0x3c163d7d,0x3d7f3bc9,0x3cacbd71,
0x3d6d3cc4,0x3d3ebd2c,0xbc95bd75,0xbd7dbc16,0xbd0e3d55,0x3d043d5c,0x3d7fbbc9,0x3cacbd71,0xbd800000,0xbcdb3d67,0x3d223d46,0x3d78bc79,0x3c48bd7b,0xbd4ebd18,0xbd623cf1,0x3b493d80,
0x3cc43d6d,0x3d803b49,0x3cf1bd62,0xbd18bd4e,0xbd7b3c48,0xbc793d78,0x3d463d22,0x3d67bcdb,0xbd35bd35,0xbd713cac,0xbbc93d7f,0x3d5c3d04,0x3d55bd0e,0xbc16bd7d,0xbd75bc95,0xbd2c3d3e,
0xbc48bd7b,0xbd67bcdb,0xbd623cf1,0xbc163d7d,0xbcc43d6d,0x3d043d5c,0x3d7f3bc9,0x3d2cbd3e,0x3d55bd0e,0x3b49bd80,0xbd46bd22,0xbd783c79,0xbd800000,0xbd183d4e,0x3c953d75,0x3d713cac,
0xbd0e3d55,0x3cac3d71,0x3d753c95,0x3d4ebd18,0x3d6dbcc4,0x3c79bd78,0xbd22bd46,0xbd803b49,0xbd7bbc48,0xbd3e3d2c,0x3bc93d7f,0x3d5c3d04,0x3d353d35,0x3d7dbc16,0x3cf1bd62,0xbcdbbd67,
0xbd35bd35,0xbd80bb49,0xbd463d22,0xbc163d7d,0x3d0e3d55,0x3d783c79,0x3d62bcf1,0x3cacbd71,0xbcc4bd6d,0xbd67bcdb,0xbd753c95,0xbd043d5c,0x3c483d7b,0x3d4e3d18,0x3d7fbbc9,0x3d2cbd3e,
0xbd800000,0xbd3e3d2c,0xbbc93d7f,0x3d183d4e,0x3d7b3c48,0x3d5cbd04,0x3c95bd75,0xbcdbbd67,0xbd6dbcc4,0xbd713cac,0xbcf13d62,0x3c793d78,0x3d553d0e,0x3d7dbc16,0x3d22bd46,0xbb49bd80,
0x3c48bd7b,0xbcacbd71,0xbd46bd22,0xbd7dbc16,0x3d353d35,0x3d783c79,0x3d75bc95,0x3d2cbd3e,0x3d553d0e,0x3d803b49,0x3d62bcf1,0x3d04bd5c,0xbd6d3cc4,0xbd183d4e,0xbbc93d7f,0x3cdb3d67,
0x3d0e3d55,0x3d673cdb,0x3d7fbbc9,0x3d4ebd18,0xbd800000,0xbd5c3d04,0xbcf13d62,0x3b493d80,0xbd7b3c48,0xbd3e3d2c,0xbc953d75,0x3c793d78,0x3cc4bd6d,0xbc16bd7d,0xbd22bd46,0xbd71bcac,
0x3cc43d6d,0x3d2c3d3e,0x3d623cf1,0x3d7d3c16,0x3d7bbc48,0x3d5cbd04,0x3d22bd46,0x3cacbd71,0xbd35bd35,0xbd67bcdb,0xbd7fbbc9,0xbd783c79,0xbd553d0e,0xbd183d4e,0xbc953d75,0x3b493d80,
0x3d6d3cc4,0x3d803b49,0x3d75bc95,0x3d4ebd18,0x3d0ebd55,0x3c79bd78,0xbbc9bd7f,0xbcdbbd67,0xbd800000,0xbd713cac,0xbd463d22,0xbd043d5c,0xbc483d7b,0x3c163d7d,0x3cf13d62,0x3d3e3d2c,
0x3d0ebd55,0x3cdbbd67,0x3c95bd75,0x3c16bd7d,0x3d6dbcc4,0x3d5cbd04,0x3d46bd22,0x3d2cbd3e,0x3d7b3c48,0x3d803b49,0x3d7fbbc9,0x3d78bc79,0x3d353d35,0x3d4e3d18,0x3d623cf1,0x3d713cac,
0x3c483d7b,0x3cac3d71,0x3cf13d62,0x3d183d4e,0xbcc43d6d,0xbc793d78,0xbbc93d7f,0x3b493d80,0xbd553d0e,0xbd3e3d2c,0xbd223d46,0xbd043d5c,0xbd800000,0xbd7d3c16,0xbd753c95,0xbd673cdb,
0x3d80,0xbbc93d7f,0xbc483d7b,0xbc953d75,0xbcc43d6d,0xbcf13d62,0xbd0e3d55,0xbd223d46,0xbd353d35,0xbd463d22,0xbd553d0e,0xbd623cf1,0xbd6d3cc4,0xbd753c95,0xbd7b3c48,0xbd7f3bc9,
0xbd800000,0xbd7fbbc9,0xbd7bbc48,0xbd75bc95,0xbd6dbcc4,0xbd62bcf1,0xbd55bd0e,0xbd46bd22,0xbd35bd35,0xbd22bd46,0xbd0ebd55,0xbcf1bd62,0xbcc4bd6d,0xbc95bd75,0xbc48bd7b,0xbbc9bd7f,
0xbd6d3cc4,0xbd7f3bc9,0xbd7bbc48,0xbd62bcf1,0x3d80,0xbc953d75,0xbd0e3d55,0xbd463d22,0x3cc4bd6d,0x3d22bd46,0x3d55bd0e,0x3d75bc95,0xbd35bd35,0xbcf1bd62,0xbc48bd7b,0x3bc9bd7f,
0x3cc43d6d,0x3bc93d7f,0xbc483d7b,0xbcf13d62,0x3d800000,0x3d753c95,0x3d553d0e,0x3d223d46,0xbd6dbcc4,0xbd46bd22,0xbd0ebd55,0xbc95bd75,0xbd353d35,0xbd623cf1,0xbd7b3c48,0xbd7fbbc9,
0x3d35bd35,0x3d75bc95,0x3d7b3c48,0x3d463d22,0x3cc43d6d,0xbbc93d7f,0xbd0e3d55,0xbd623cf1,0x3d80,0xbcf13d62,0xbd553d0e,0xbd7f3bc9,0xbd6dbcc4,0xbd22bd46,0xbc48bd7b,0x3c95bd75,
0x3d353d35,0x3c953d75,0xbc483d7b,0xbd223d46,0xbd6d3cc4,0xbd7fbbc9,0xbd55bd0e,0xbcf1bd62,0xbd800000,0xbd62bcf1,0xbd0ebd55,0xbbc9bd7f,0x3cc4bd6d,0x3d46bd22,0x3d7bbc48,0x3d753c95,
0xbd6dbcc4,0xbcf1bd62,0x3c48bd7b,0x3d46bd22,0x3d353d35,0x3bc93d7f,0xbd0e3d55,0xbd753c95,0xbcc4bd6d,0x3c95bd75,0x3d55bd0e,0x3d7f3bc9,0x3d80,0xbd223d46,0xbd7b3c48,0xbd62bcf1,
0xbcc43d6d,0xbd623cf1,0xbd7bbc48,0xbd22bd46,0x3d35bd35,0x3d7fbbc9,0x3d553d0e,0x3c953d75,0xbd6d3cc4,0xbd75bc95,0xbd0ebd55,0x3bc9bd7f,0x3d800000,0x3d463d22,0x3c483d7b,0xbcf13d62,
0xbd800000,0xbd22bd46,0x3c48bd7b,0x3d62bcf1,0x3d6d3cc4,0x3c953d75,0xbd0e3d55,0xbd7f3bc9,0xbd35bd35,0x3bc9bd7f,0x3d55bd0e,0x3d753c95,0x3cc43d6d,0xbcf13d62,0xbd7b3c48,0xbd46bd22,
0x3d80,0xbd463d22,0xbd7bbc48,0xbcf1bd62,0x3cc4bd6d,0x3d75bc95,0x3d553d0e,0x3bc93d7f,0xbd353d35,0xbd7fbbc9,0xbd0ebd55,0x3c95bd75,0x3d6dbcc4,0x3d623cf1,0x3c483d7b,0xbd223d46,
0xbcc4bd6d,0x3d22bd46,0x3d7b3c48,0x3c953d75,0x3d800000,0x3cf13d62,0xbd0e3d55,0xbd7fbbc9,0x3d6d3cc4,0x3bc93d7f,0xbd553d0e,0xbd62bcf1,0xbd353d35,0xbd75bc95,0xbc48bd7b,0x3d46bd22,
0x3d6dbcc4,0x3d463d22,0xbc483d7b,0xbd753c95,0x3d80,0xbd623cf1,0xbd55bd0e,0x3bc9bd7f,0xbcc43d6d,0xbd7f3bc9,0xbd0ebd55,0x3cf1bd62,0xbd35bd35,0x3c95bd75,0x3d7bbc48,0x3d223d46,
0x3d353d35,0xbcf13d62,0xbd7bbc48,0xbbc9bd7f,0x3d6dbcc4,0x3d223d46,0xbd0e3d55,0xbd75bc95,0xbd800000,0xbc95bd75,0x3d55bd0e,0x3d463d22,0xbcc43d6d,0xbd7fbbc9,0xbc48bd7b,0x3d62bcf1,
0x3d35bd35,0x3d623cf1,0xbc483d7b,0xbd7f3bc9,0xbcc4bd6d,0x3d46bd22,0x3d553d0e,0xbc953d75,0x3d80,0xbd753c95,0xbd0ebd55,0x3d22bd46,0x3d6d3cc4,0xbbc93d7f,0xbd7b3c48,0xbcf1bd62,
0x3cc4bd6d,0x3d753c95,0xbc483d7b,0xbd7fbbc9,0x3d35bd35,0x3d463d22,0xbd0e3d55,0xbd62bcf1,0x3d6dbcc4,0x3cf13d62,0xbd553d0e,0xbd22bd46,0x3d800000,0x3bc93d7f,0xbd7b3c48,0xbc95bd75,
0x3d6d3cc4,0xbc953d75,0xbd7bbc48,0x3bc9bd7f,0x3d353d35,0xbd223d46,0xbd55bd0e,0x3cf1bd62,0x3cc43d6d,0xbd623cf1,0xbd0ebd55,0x3d46bd22,0x3d80,0xbd7f3bc9,0xbc48bd7b,0x3d75bc95,
0xbd800000,0xbd7fbbc9,0xbd7bbc48,0xbd75bc95,0xbd6dbcc4,0xbd62bcf1,0xbd55bd0e,0xbd46bd22,0xbd35bd35,0xbd22bd46,0xbd0ebd55,0xbcf1bd62,0xbcc4bd6d,0xbc95bd75,0xbc48bd7b,0xbbc9bd7f,
0x8000bd80,0x3bc9bd7f,0x3c48bd7b,0x3c95bd75,0x3cc4bd6d,0x3cf1bd62,0x3d0ebd55,0x3d22bd46,0x3d35bd35,0x3d46bd22,0x3d55bd0e,0x3d62bcf1,0x3d6dbcc4,0x3d75bc95,0x3d7bbc48,0x3d7fbbc9,
0xbcc4bd6d,0xbbc9bd7f,0x3c48bd7b,0x3cf1bd62,0xbd800000,0xbd75bc95,0xbd55bd0e,0xbd22bd46,0x3d6d3cc4,0x3d463d22,0x3d0e3d55,0x3c953d75,0x3d35bd35,0x3d62bcf1,0x3d7bbc48,0x3d7f3bc9,
0xbd6d3cc4,0xbd7f3bc9,0xbd7bbc48,0xbd62bcf1,0x80003d80,0xbc953d75,0xbd0e3d55,0xbd463d22,0x3cc4bd6d,0x3d22bd46,0x3d55bd0e,0x3d75bc95,0xbd35bd35,0xbcf1bd62,0xbc48bd7b,0x3bc9bd7f,
0x3d353d35,0x3c953d75,0xbc483d7b,0xbd223d46,0xbd6d3cc4,0xbd7fbbc9,0xbd55bd0e,0xbcf1bd62,0xbd800000,0xbd62bcf1,0xbd0ebd55,0xbbc9bd7f,0x3cc4bd6d,0x3d46bd22,0x3d7bbc48,0x3d753c95,
0xbd353d35,0xbd753c95,0xbd7bbc48,0xbd46bd22,0xbcc4bd6d,0x3bc9bd7f,0x3d0ebd55,0x3d62bcf1,0x8000bd80,0x3cf1bd62,0x3d55bd0e,0x3d7fbbc9,0x3d6d3cc4,0x3d223d46,0x3c483d7b,0xbc953d75,
0x3cc4bd6d,0x3d62bcf1,0x3d7b3c48,0x3d223d46,0xbd353d35,0xbd7f3bc9,0xbd55bd0e,0xbc95bd75,0x3d6dbcc4,0x3d753c95,0x3d0e3d55,0xbbc93d7f,0xbd800000,0xbd46bd22,0xbc48bd7b,0x3cf1bd62,
0xbd6dbcc4,0xbcf1bd62,0x3c48bd7b,0x3d46bd22,0x3d353d35,0x3bc93d7f,0xbd0e3d55,0xbd753c95,0xbcc4bd6d,0x3c95bd75,0x3d55bd0e,0x3d7f3bc9,0x80003d80,0xbd223d46,0xbd7b3c48,0xbd62bcf1,
0x8000bd80,0x3d46bd22,0x3d7b3c48,0x3cf13d62,0xbcc43d6d,0xbd753c95,0xbd55bd0e,0xbbc9bd7f,0x3d35bd35,0x3d7f3bc9,0x3d0e3d55,0xbc953d75,0xbd6d3cc4,0xbd62bcf1,0xbc48bd7b,0x3d22bd46,
0xbd800000,0xbd22bd46,0x3c48bd7b,0x3d62bcf1,0x3d6d3cc4,0x3c953d75,0xbd0e3d55,0xbd7f3bc9,0xbd35bd35,0x3bc9bd7f,0x3d55bd0e,0x3d753c95,0x3cc43d6d,0xbcf13d62,0xbd7b3c48,0xbd46bd22,
0x3d6dbcc4,0x3d463d22,0xbc483d7b,0xbd753c95,0x80003d80,0xbd623cf1,0xbd55bd0e,0x3bc9bd7f,0xbcc43d6d,0xbd7f3bc9,0xbd0ebd55,0x3cf1bd62,0xbd35bd35,0x3c95bd75,0x3d7bbc48,0x3d223d46,
0x3cc43d6d,0xbd223d46,0xbd7bbc48,0xbc95bd75,0xbd800000,0xbcf1bd62,0x3d0ebd55,0x3d7f3bc9,0xbd6dbcc4,0xbbc9bd7f,0x3d55bd0e,0x3d623cf1,0x3d35bd35,0x3d753c95,0x3c483d7b,0xbd463d22,
0xbd353d35,0xbd62bcf1,0x3c48bd7b,0x3d7fbbc9,0x3cc43d6d,0xbd463d22,0xbd55bd0e,0x3c95bd75,0x8000bd80,0x3d75bc95,0x3d0e3d55,0xbd223d46,0xbd6dbcc4,0x3bc9bd7f,0x3d7bbc48,0x3cf13d62,
0x3d353d35,0xbcf13d62,0xbd7bbc48,0xbbc9bd7f,0x3d6dbcc4,0x3d223d46,0xbd0e3d55,0xbd75bc95,0xbd800000,0xbc95bd75,0x3d55bd0e,0x3d463d22,0xbcc43d6d,0xbd7fbbc9,0xbc48bd7b,0x3d62bcf1,
0x3d6d3cc4,0xbc953d75,0xbd7bbc48,0x3bc9bd7f,0x3d353d35,0xbd223d46,0xbd55bd0e,0x3cf1bd62,0x3cc43d6d,0xbd623cf1,0xbd0ebd55,0x3d46bd22,0x80003d80,0xbd7f3bc9,0xbc48bd7b,0x3d75bc95,
0xbcc43d6d,0xbd75bc95,0x3c48bd7b,0x3d7f3bc9,0xbd353d35,0xbd46bd22,0x3d0ebd55,0x3d623cf1,0xbd6d3cc4,0xbcf1bd62,0x3d55bd0e,0x3d223d46,0xbd800000,0xbbc9bd7f,0x3d7bbc48,0x3c953d75,
0x3d80,0xbd7fbbc9,0x3c48bd7b,0x3d753c95,0xbcc43d6d,0xbd62bcf1,0x3d0ebd55,0x3d463d22,0xbd353d35,0xbd22bd46,0x3d55bd0e,0x3cf13d62,0xbd6d3cc4,0xbc95bd75,0x3d7bbc48,0x3bc93d7f,
0xbd800000,0x3bc9bd7f,0x3d7b3c48,0xbc953d75,0xbd6dbcc4,0x3cf1bd62,0x3d553d0e,0xbd223d46,0xbd35bd35,0x3d46bd22,0x3d0e3d55,0xbd623cf1,0xbcc4bd6d,0x3d75bc95,0x3c483d7b,0xbd7f3bc9,
0xbd6d3cc4,0xbbc9bd7f,0x3d7b3c48,0xbcf13d62,0x3d80,0xbd75bc95,0x3d0ebd55,0x3d223d46,0x3cc4bd6d,0x3d463d22,0xbd553d0e,0xbc95bd75,0xbd35bd35,0x3d62bcf1,0x3c483d7b,0xbd7fbbc9,
0x3cc43d6d,0xbd7f3bc9,0x3c48bd7b,0x3d623cf1,0x3d800000,0xbc953d75,0xbd55bd0e,0x3d46bd22,0xbd6dbcc4,0x3d22bd46,0x3d0e3d55,0xbd753c95,0xbd353d35,0xbcf1bd62,0x3d7bbc48,0xbbc93d7f,
0x3d35bd35,0x3c953d75,0xbd7bbc48,0x3d22bd46,0x3cc43d6d,0xbd7fbbc9,0x3d0ebd55,0x3cf13d62,0x3d80,0xbd62bcf1,0x3d55bd0e,0x3bc93d7f,0xbd6dbcc4,0x3d46bd22,0x3c483d7b,0xbd75bc95,
0x3d353d35,0xbd753c95,0x3c48bd7b,0x3d463d22,0xbd6d3cc4,0x3bc9bd7f,0x3d553d0e,0xbd623cf1,0xbd800000,0x3cf1bd62,0x3d0e3d55,0xbd7f3bc9,0x3cc4bd6d,0x3d223d46,0xbd7b3c48,0x3c95bd75,
0xbd6dbcc4,0x3d62bcf1,0xbc483d7b,0xbd22bd46,0x3d353d35,0xbd7f3bc9,0x3d0ebd55,0x3c953d75,0xbcc4bd6d,0x3d753c95,0xbd553d0e,0x3bc9bd7f,0x3d80,0xbd46bd22,0x3d7bbc48,0xbcf13d62,
0xbcc43d6d,0xbcf1bd62,0x3d7b3c48,0xbd463d22,0x3d35bd35,0x3bc93d7f,0xbd55bd0e,0x3d75bc95,0xbd6d3cc4,0x3c95bd75,0x3d0e3d55,0xbd7fbbc9,0x3d800000,0xbd223d46,0xbc48bd7b,0x3d623cf1,
0xbd800000,0x3d46bd22,0xbc483d7b,0xbcf1bd62,0x3d6d3cc4,0xbd753c95,0x3d0ebd55,0x3bc93d7f,0xbd35bd35,0x3d7f3bc9,0xbd553d0e,0x3c95bd75,0x3cc43d6d,0xbd62bcf1,0x3d7bbc48,0xbd223d46,
0x3d80,0xbd22bd46,0x3d7b3c48,0xbd623cf1,0x3cc4bd6d,0x3c953d75,0xbd55bd0e,0x3d7fbbc9,0xbd353d35,0x3bc9bd7f,0x3d0e3d55,0xbd75bc95,0x3d6dbcc4,0xbcf13d62,0xbc48bd7b,0x3d463d22,
0xbcc4bd6d,0x3d463d22,0xbd7bbc48,0x3d75bc95,0x3d800000,0xbd623cf1,0x3d0ebd55,0xbbc93d7f,0x3d6d3cc4,0xbd7f3bc9,0x3d55bd0e,0xbcf13d62,0xbd353d35,0x3c95bd75,0x3c483d7b,0xbd22bd46,
0x3d6dbcc4,0xbd223d46,0x3c48bd7b,0x3c953d75,0x3d80,0xbcf1bd62,0x3d553d0e,0xbd7fbbc9,0xbcc43d6d,0xbbc9bd7f,0x3d0e3d55,0xbd62bcf1,0xbd35bd35,0x3d753c95,0xbd7b3c48,0x3d46bd22,
0x3d353d35,0xbd62bcf1,0x3d7b3c48,0xbd7f3bc9,0x3d6dbcc4,0xbd463d22,0x3d0ebd55,0xbc953d75,0xbd800000,0x3d75bc95,0xbd553d0e,0x3d22bd46,0xbcc43d6d,0x3bc9bd7f,0x3c483d7b,0xbcf1bd62,
0x3d35bd35,0xbcf13d62,0x3c48bd7b,0x3bc93d7f,0xbcc4bd6d,0x3d223d46,0xbd55bd0e,0x3d753c95,0x3d80,0xbc95bd75,0x3d0e3d55,0xbd46bd22,0x3d6d3cc4,0xbd7fbbc9,0x3d7bbc48,0xbd623cf1,
0x3cc4bd6d,0xbc953d75,0x3c48bd7b,0xbbc93d7f,0x3d35bd35,0xbd223d46,0x3d0ebd55,0xbcf13d62,0x3d6dbcc4,0xbd623cf1,0x3d55bd0e,0xbd463d22,0x3d800000,0xbd7f3bc9,0x3d7bbc48,0xbd753c95,
0x3d6d3cc4,0xbd75bc95,0x3d7b3c48,0xbd7fbbc9,0x3d353d35,0xbd46bd22,0x3d553d0e,0xbd62bcf1,0x3cc43d6d,0xbcf1bd62,0x3d0e3d55,0xbd22bd46,0x3d80,0xbbc9bd7f,0x3c483d7b,0xbc95bd75,
0xbd800000,0x3bc9bd7f,0x3d7b3c48,0xbc953d75,0xbd6dbcc4,0x3cf1bd62,0x3d553d0e,0xbd223d46,0xbd35bd35,0x3d46bd22,0x3d0e3d55,0xbd623cf1,0xbcc4bd6d,0x3d75bc95,0x3c483d7b,0xbd7f3bc9,
0x8000bd80,0x3d7f3bc9,0xbc483d7b,0xbd75bc95,0x3cc4bd6d,0x3d623cf1,0xbd0e3d55,0xbd46bd22,0x3d35bd35,0x3d223d46,0xbd553d0e,0xbcf1bd62,0x3d6dbcc4,0x3c953d75,0xbd7b3c48,0xbbc9bd7f,
0xbcc4bd6d,0x3d7fbbc9,0xbc483d7b,0xbd62bcf1,0xbd800000,0x3c95bd75,0x3d553d0e,0xbd463d22,0x3d6d3cc4,0xbd223d46,0xbd0ebd55,0x3d75bc95,0x3d35bd35,0x3cf13d62,0xbd7b3c48,0x3bc9bd7f,
0xbd6d3cc4,0xbbc9bd7f,0x3d7b3c48,0xbcf13d62,0x80003d80,0xbd75bc95,0x3d0ebd55,0x3d223d46,0x3cc4bd6d,0x3d463d22,0xbd553d0e,0xbc95bd75,0xbd35bd35,0x3d62bcf1,0x3c483d7b,0xbd7fbbc9,
0x3d353d35,0xbd753c95,0x3c48bd7b,0x3d463d22,0xbd6d3cc4,0x3bc9bd7f,0x3d553d0e,0xbd623cf1,0xbd800000,0x3cf1bd62,0x3d0e3d55,0xbd7f3bc9,0x3cc4bd6d,0x3d223d46,0xbd7b3c48,0x3c95bd75,
0xbd353d35,0xbc95bd75,0x3d7b3c48,0xbd223d46,0xbcc4bd6d,0x3d7f3bc9,0xbd0e3d55,0xbcf1bd62,0x8000bd80,0x3d623cf1,0xbd553d0e,0xbbc9bd7f,0x3d6d3cc4,0xbd463d22,0xbc48bd7b,0x3d753c95,
0x3cc4bd6d,0x3cf13d62,0xbd7bbc48,0x3d46bd22,0xbd353d35,0xbbc9bd7f,0x3d553d0e,0xbd753c95,0x3d6dbcc4,0xbc953d75,0xbd0ebd55,0x3d7f3bc9,0xbd800000,0x3d22bd46,0x3c483d7b,0xbd62bcf1,
0xbd6dbcc4,0x3d62bcf1,0xbc483d7b,0xbd22bd46,0x3d353d35,0xbd7f3bc9,0x3d0ebd55,0x3c953d75,0xbcc4bd6d,0x3d753c95,0xbd553d0e,0x3bc9bd7f,0x80003d80,0xbd46bd22,0x3d7bbc48,0xbcf13d62,
0x8000bd80,0x3d223d46,0xbd7bbc48,0x3d62bcf1,0xbcc43d6d,0xbc95bd75,0x3d553d0e,0xbd7f3bc9,0x3d35bd35,0xbbc93d7f,0xbd0ebd55,0x3d753c95,0xbd6d3cc4,0x3cf1bd62,0x3c483d7b,0xbd46bd22,
0xbd800000,0x3d46bd22,0xbc483d7b,0xbcf1bd62,0x3d6d3cc4,0xbd753c95,0x3d0ebd55,0x3bc93d7f,0xbd35bd35,0x3d7f3bc9,0xbd553d0e,0x3c95bd75,0x3cc43d6d,0xbd62bcf1,0x3d7bbc48,0xbd223d46,
0x3d6dbcc4,0xbd223d46,0x3c48bd7b,0x3c953d75,0x80003d80,0xbcf1bd62,0x3d553d0e,0xbd7fbbc9,0xbcc43d6d,0xbbc9bd7f,0x3d0e3d55,0xbd62bcf1,0xbd35bd35,0x3d753c95,0xbd7b3c48,0x3d46bd22,
0x3cc43d6d,0xbd46bd22,0x3d7b3c48,0xbd753c95,0xbd800000,0x3d62bcf1,0xbd0e3d55,0x3bc9bd7f,0xbd6dbcc4,0x3d7fbbc9,0xbd553d0e,0x3cf1bd62,0x3d35bd35,0xbc953d75,0xbc48bd7b,0x3d223d46,
0xbd353d35,0x3cf1bd62,0xbc483d7b,0xbbc9bd7f,0x3cc43d6d,0xbd22bd46,0x3d553d0e,0xbd75bc95,0x8000bd80,0x3c953d75,0xbd0ebd55,0x3d463d22,0xbd6dbcc4,0x3d7f3bc9,0xbd7b3c48,0x3d62bcf1,
0x3d353d35,0xbd62bcf1,0x3d7b3c48,0xbd7f3bc9,0x3d6dbcc4,0xbd463d22,0x3d0ebd55,0xbc953d75,0xbd800000,0x3d75bc95,0xbd553d0e,0x3d22bd46,0xbcc43d6d,0x3bc9bd7f,0x3c483d7b,0xbcf1bd62,
0x3d6d3cc4,0xbd75bc95,0x3d7b3c48,0xbd7fbbc9,0x3d353d35,0xbd46bd22,0x3d553d0e,0xbd62bcf1,0x3cc43d6d,0xbcf1bd62,0x3d0e3d55,0xbd22bd46,0x80003d80,0xbbc9bd7f,0x3c483d7b,0xbc95bd75,
0xbcc43d6d,0x3c95bd75,0xbc483d7b,0x3bc9bd7f,0xbd353d35,0x3d22bd46,0xbd0e3d55,0x3cf1bd62,0xbd6d3cc4,0x3d62bcf1,0xbd553d0e,0x3d46bd22,0xbd800000,0x3d7fbbc9,0xbd7b3c48,0x3d75bc95,
0x3d80,0x3bc9bd7f,0xbc483d7b,0x3c95bd75,0xbcc43d6d,0x3cf1bd62,0xbd0e3d55,0x3d22bd46,0xbd353d35,0x3d46bd22,0xbd553d0e,0x3d62bcf1,0xbd6d3cc4,0x3d75bc95,0xbd7b3c48,0x3d7fbbc9,
0xbd800000,0x3d7f3bc9,0xbd7bbc48,0x3d753c95,0xbd6dbcc4,0x3d623cf1,0xbd55bd0e,0x3d463d22,0xbd35bd35,0x3d223d46,0xbd0ebd55,0x3cf13d62,0xbcc4bd6d,0x3c953d75,0xbc48bd7b,0x3bc93d7f,
0xbd6d3cc4,0x3d7fbbc9,0xbd7bbc48,0x3d623cf1,0x3d80,0x3c95bd75,0xbd0e3d55,0x3d46bd22,0x3cc4bd6d,0xbd223d46,0x3d55bd0e,0xbd753c95,0xbd35bd35,0x3cf13d62,0xbc48bd7b,0xbbc93d7f,
0x3cc43d6d,0xbbc9bd7f,0xbc483d7b,0x3cf1bd62,0x3d800000,0xbd75bc95,0x3d553d0e,0xbd22bd46,0xbd6dbcc4,0x3d463d22,0xbd0ebd55,0x3c953d75,0xbd353d35,0x3d62bcf1,0xbd7b3c48,0x3d7f3bc9,
0x3d35bd35,0xbd753c95,0x3d7b3c48,0xbd46bd22,0x3cc43d6d,0x3bc9bd7f,0xbd0e3d55,0x3d62bcf1,0x3d80,0x3cf1bd62,0xbd553d0e,0x3d7fbbc9,0xbd6dbcc4,0x3d223d46,0xbc48bd7b,0xbc953d75,
0x3d353d35,0xbc95bd75,0xbc483d7b,0x3d22bd46,0xbd6d3cc4,0x3d7f3bc9,0xbd55bd0e,0x3cf13d62,0xbd800000,0x3d623cf1,0xbd0ebd55,0x3bc93d7f,0x3cc4bd6d,0xbd463d22,0x3d7bbc48,0xbd75bc95,
0xbd6dbcc4,0x3cf13d62,0x3c48bd7b,0xbd463d22,0x3d353d35,0xbbc9bd7f,0xbd0e3d55,0x3d75bc95,0xbcc4bd6d,0xbc953d75,0x3d55bd0e,0xbd7fbbc9,0x3d80,0x3d22bd46,0xbd7b3c48,0x3d623cf1,
0xbcc43d6d,0x3d62bcf1,0xbd7bbc48,0x3d223d46,0x3d35bd35,0xbd7f3bc9,0x3d553d0e,0xbc95bd75,0xbd6d3cc4,0x3d753c95,0xbd0ebd55,0xbbc93d7f,0x3d800000,0xbd46bd22,0x3c483d7b,0x3cf1bd62,
0xbd800000,0x3d223d46,0x3c48bd7b,0xbd623cf1,0x3d6d3cc4,0xbc95bd75,0xbd0e3d55,0x3d7fbbc9,0xbd35bd35,0xbbc93d7f,0x3d55bd0e,0xbd75bc95,0x3cc43d6d,0x3cf1bd62,0xbd7b3c48,0x3d463d22,
0x3d80,0x3d46bd22,0xbd7bbc48,0x3cf13d62,0x3cc4bd6d,0xbd753c95,0x3d553d0e,0xbbc9bd7f,0xbd353d35,0x3d7f3bc9,0xbd0ebd55,0xbc953d75,0x3d6dbcc4,0xbd62bcf1,0x3c483d7b,0x3d22bd46,
0xbcc4bd6d,0xbd223d46,0x3d7b3c48,0xbc95bd75,0x3d800000,0xbcf1bd62,0xbd0e3d55,0x3d7f3bc9,0x3d6d3cc4,0xbbc9bd7f,0xbd553d0e,0x3d623cf1,0xbd353d35,0x3d753c95,0xbc48bd7b,0xbd463d22,
0x3d6dbcc4,0xbd46bd22,0xbc483d7b,0x3d75bc95,0x3d80,0x3d62bcf1,0xbd55bd0e,0xbbc93d7f,0xbcc43d6d,0x3d7fbbc9,0xbd0ebd55,0xbcf13d62,0xbd35bd35,0xbc953d75,0x3d7bbc48,0xbd22bd46,
0x3d353d35,0x3cf1bd62,0xbd7bbc48,0x3bc93d7f,0x3d6dbcc4,0xbd22bd46,0xbd0e3d55,0x3d753c95,0xbd800000,0x3c953d75,0x3d55bd0e,0xbd46bd22,0xbcc43d6d,0x3d7f3bc9,0xbc48bd7b,0xbd623cf1,
0x3d35bd35,0xbd62bcf1,0xbc483d7b,0x3d7fbbc9,0xbcc4bd6d,0xbd463d22,0x3d553d0e,0x3c95bd75,0x3d80,0x3d75bc95,0xbd0ebd55,0xbd223d46,0x3d6d3cc4,0x3bc9bd7f,0xbd7b3c48,0x3cf13d62,
0x3cc4bd6d,0xbd75bc95,0xbc483d7b,0x3d7f3bc9,0x3d35bd35,0xbd46bd22,0xbd0e3d55,0x3d623cf1,0x3d6dbcc4,0xbcf1bd62,0xbd553d0e,0x3d223d46,0x3d800000,0xbbc9bd7f,0xbd7b3c48,0x3c953d75,
0x3d6d3cc4,0x3c95bd75,0xbd7bbc48,0xbbc93d7f,0x3d353d35,0x3d22bd46,0xbd55bd0e,0xbcf13d62,0x3cc43d6d,0x3d62bcf1,0xbd0ebd55,0xbd463d22,0x3d80,0x3d7fbbc9,0xbc48bd7b,0xbd753c95,
0xbd800000,0x3d7f3bc9,0xbd7bbc48,0x3d753c95,0xbd6dbcc4,0x3d623cf1,0xbd55bd0e,0x3d463d22,0xbd35bd35,0x3d223d46,0xbd0ebd55,0x3cf13d62,0xbcc4bd6d,0x3c953d75,0xbc48bd7b,0x3bc93d7f,
0x8000bd80,0xbbc93d7f,0x3c48bd7b,0xbc953d75,0x3cc4bd6d,0xbcf13d62,0x3d0ebd55,0xbd223d46,0x3d35bd35,0xbd463d22,0x3d55bd0e,0xbd623cf1,0x3d6dbcc4,0xbd753c95,0x3d7bbc48,0xbd7f3bc9,
0xbcc4bd6d,0x3bc93d7f,0x3c48bd7b,0xbcf13d62,0xbd800000,0x3d753c95,0xbd55bd0e,0x3d223d46,0x3d6d3cc4,0xbd46bd22,0x3d0e3d55,0xbc95bd75,0x3d35bd35,0xbd623cf1,0x3d7bbc48,0xbd7fbbc9,
0xbd6d3cc4,0x3d7fbbc9,0xbd7bbc48,0x3d623cf1,0x80003d80,0x3c95bd75,0xbd0e3d55,0x3d46bd22,0x3cc4bd6d,0xbd223d46,0x3d55bd0e,0xbd753c95,0xbd35bd35,0x3cf13d62,0xbc48bd7b,0xbbc93d7f,
0x3d353d35,0xbc95bd75,0xbc483d7b,0x3d22bd46,0xbd6d3cc4,0x3d7f3bc9,0xbd55bd0e,0x3cf13d62,0xbd800000,0x3d623cf1,0xbd0ebd55,0x3bc93d7f,0x3cc4bd6d,0xbd463d22,0x3d7bbc48,0xbd75bc95,
0xbd353d35,0x3d75bc95,0xbd7bbc48,0x3d463d22,0xbcc4bd6d,0xbbc93d7f,0x3d0ebd55,0xbd623cf1,0x8000bd80,0xbcf13d62,0x3d55bd0e,0xbd7f3bc9,0x3d6d3cc4,0xbd22bd46,0x3c483d7b,0x3c95bd75,
0x3cc4bd6d,0xbd623cf1,0x3d7b3c48,0xbd22bd46,0xbd353d35,0x3d7fbbc9,0xbd55bd0e,0x3c953d75,0x3d6dbcc4,0xbd75bc95,0x3d0e3d55,0x3bc9bd7f,0xbd800000,0x3d463d22,0xbc48bd7b,0xbcf13d62,
0xbd6dbcc4,0x3cf13d62,0x3c48bd7b,0xbd463d22,0x3d353d35,0xbbc9bd7f,0xbd0e3d55,0x3d75bc95,0xbcc4bd6d,0xbc953d75,0x3d55bd0e,0xbd7fbbc9,0x80003d80,0x3d22bd46,0xbd7b3c48,0x3d623cf1,
0x8000bd80,0xbd463d22,0x3d7b3c48,0xbcf1bd62,0xbcc43d6d,0x3d75bc95,0xbd55bd0e,0x3bc93d7f,0x3d35bd35,0xbd7fbbc9,0x3d0e3d55,0x3c95bd75,0xbd6d3cc4,0x3d623cf1,0xbc48bd7b,0xbd223d46,
0xbd800000,0x3d223d46,0x3c48bd7b,0xbd623cf1,0x3d6d3cc4,0xbc95bd75,0xbd0e3d55,0x3d7fbbc9,0xbd35bd35,0xbbc93d7f,0x3d55bd0e,0xbd75bc95,0x3cc43d6d,0x3cf1bd62,0xbd7b3c48,0x3d463d22,
0x3d6dbcc4,0xbd46bd22,0xbc483d7b,0x3d75bc95,0x80003d80,0x3d62bcf1,0xbd55bd0e,0xbbc93d7f,0xbcc43d6d,0x3d7fbbc9,0xbd0ebd55,0xbcf13d62,0xbd35bd35,0xbc953d75,0x3d7bbc48,0xbd22bd46,
0x3cc43d6d,0x3d22bd46,0xbd7bbc48,0x3c953d75,0xbd800000,0x3cf13d62,0x3d0ebd55,0xbd7fbbc9,0xbd6dbcc4,0x3bc93d7f,0x3d55bd0e,0xbd62bcf1,0x3d35bd35,0xbd75bc95,0x3c483d7b,0x3d46bd22,
0xbd353d35,0x3d623cf1,0x3c48bd7b,0xbd7f3bc9,0x3cc43d6d,0x3d46bd22,0xbd55bd0e,0xbc953d75,0x8000bd80,0xbd753c95,0x3d0e3d55,0x3d22bd46,0xbd6dbcc4,0xbbc93d7f,0x3d7bbc48,0xbcf1bd62,
0x3d353d35,0x3cf1bd62,0xbd7bbc48,0x3bc93d7f,0x3d6dbcc4,0xbd22bd46,0xbd0e3d55,0x3d753c95,0xbd800000,0x3c953d75,0x3d55bd0e,0xbd46bd22,0xbcc43d6d,0x3d7f3bc9,0xbc48bd7b,0xbd623cf1,
0x3d6d3cc4,0x3c95bd75,0xbd7bbc48,0xbbc93d7f,0x3d353d35,0x3d22bd46,0xbd55bd0e,0xbcf13d62,0x3cc43d6d,0x3d62bcf1,0xbd0ebd55,0xbd463d22,0x80003d80,0x3d7fbbc9,0xbc48bd7b,0xbd753c95,
0xbcc43d6d,0x3d753c95,0x3c48bd7b,0xbd7fbbc9,0xbd353d35,0x3d463d22,0x3d0ebd55,0xbd62bcf1,0xbd6d3cc4,0x3cf13d62,0x3d55bd0e,0xbd22bd46,0xbd800000,0x3bc93d7f,0x3d7bbc48,0xbc95bd75,
0x3d80,0x3d7f3bc9,0x3c48bd7b,0xbd75bc95,0xbcc43d6d,0x3d623cf1,0x3d0ebd55,0xbd46bd22,0xbd353d35,0x3d223d46,0x3d55bd0e,0xbcf1bd62,0xbd6d3cc4,0x3c953d75,0x3d7bbc48,0xbbc9bd7f,
0xbd800000,0xbbc93d7f,0x3d7b3c48,0x3c95bd75,0xbd6dbcc4,0xbcf13d62,0x3d553d0e,0x3d22bd46,0xbd35bd35,0xbd463d22,0x3d0e3d55,0x3d62bcf1,0xbcc4bd6d,0xbd753c95,0x3c483d7b,0x3d7fbbc9,
0xbd6d3cc4,0x3bc93d7f,0x3d7b3c48,0x3cf1bd62,0x3d80,0x3d753c95,0x3d0ebd55,0xbd22bd46,0x3cc4bd6d,0xbd46bd22,0xbd553d0e,0x3c953d75,0xbd35bd35,0xbd623cf1,0x3c483d7b,0x3d7f3bc9,
0x3cc43d6d,0x3d7fbbc9,0x3c48bd7b,0xbd62bcf1,0x3d800000,0x3c95bd75,0xbd55bd0e,0xbd463d22,0xbd6dbcc4,0xbd223d46,0x3d0e3d55,0x3d75bc95,0xbd353d35,0x3cf13d62,0x3d7bbc48,0x3bc9bd7f,
0x3d35bd35,0xbc95bd75,0xbd7bbc48,0xbd223d46,0x3cc43d6d,0x3d7f3bc9,0x3d0ebd55,0xbcf1bd62,0x3d80,0x3d623cf1,0x3d55bd0e,0xbbc9bd7f,0xbd6dbcc4,0xbd463d22,0x3c483d7b,0x3d753c95,
0x3d353d35,0x3d75bc95,0x3c48bd7b,0xbd46bd22,0xbd6d3cc4,0xbbc93d7f,0x3d553d0e,0x3d62bcf1,0xbd800000,0xbcf13d62,0x3d0e3d55,0x3d7fbbc9,0x3cc4bd6d,0xbd22bd46,0xbd7b3c48,0xbc953d75,
0xbd6dbcc4,0xbd623cf1,0xbc483d7b,0x3d223d46,0x3d353d35,0x3d7fbbc9,0x3d0ebd55,0xbc95bd75,0xbcc4bd6d,0xbd75bc95,0xbd553d0e,0xbbc93d7f,0x3d80,0x3d463d22,0x3d7bbc48,0x3cf1bd62,
0xbcc43d6d,0x3cf13d62,0x3d7b3c48,0x3d46bd22,0x3d35bd35,0xbbc9bd7f,0xbd55bd0e,0xbd753c95,0xbd6d3cc4,0xbc953d75,0x3d0e3d55,0x3d7f3bc9,0x3d800000,0x3d22bd46,0xbc48bd7b,0xbd62bcf1,
0xbd800000,0xbd463d22,0xbc483d7b,0x3cf13d62,0x3d6d3cc4,0x3d75bc95,0x3d0ebd55,0xbbc9bd7f,0xbd35bd35,0xbd7fbbc9,0xbd553d0e,0xbc953d75,0x3cc43d6d,0x3d623cf1,0x3d7bbc48,0x3d22bd46,
0x3d80,0x3d223d46,0x3d7b3c48,0x3d62bcf1,0x3cc4bd6d,0xbc95bd75,0xbd55bd0e,0xbd7f3bc9,0xbd353d35,0xbbc93d7f,0x3d0e3d55,0x3d753c95,0x3d6dbcc4,0x3cf1bd62,0xbc48bd7b,0xbd46bd22,
0xbcc4bd6d,0xbd46bd22,0xbd7bbc48,0xbd753c95,0x3d800000,0x3d62bcf1,0x3d0ebd55,0x3bc9bd7f,0x3d6d3cc4,0x3d7fbbc9,0x3d55bd0e,0x3cf1bd62,0xbd353d35,0xbc953d75,0x3c483d7b,0x3d223d46,
0x3d6dbcc4,0x3d22bd46,0x3c48bd7b,0xbc95bd75,0x3d80,0x3cf13d62,0x3d553d0e,0x3d7f3bc9,0xbcc43d6d,0x3bc93d7f,0x3d0e3d55,0x3d623cf1,0xbd35bd35,0xbd75bc95,0xbd7b3c48,0xbd463d22,
0x3d353d35,0x3d623cf1,0x3d7b3c48,0x3d7fbbc9,0x3d6dbcc4,0x3d46bd22,0x3d0ebd55,0x3c95bd75,0xbd800000,0xbd753c95,0xbd553d0e,0xbd223d46,0xbcc43d6d,0xbbc93d7f,0x3c483d7b,0x3cf13d62,
0x3d35bd35,0x3cf1bd62,0x3c48bd7b,0xbbc9bd7f,0xbcc4bd6d,0xbd22bd46,0xbd55bd0e,0xbd75bc95,0x3d80,0x3c953d75,0x3d0e3d55,0x3d463d22,0x3d6d3cc4,0x3d7f3bc9,0x3d7bbc48,0x3d62bcf1,
0x3cc4bd6d,0x3c95bd75,0x3c48bd7b,0x3bc9bd7f,0x3d35bd35,0x3d22bd46,0x3d0ebd55,0x3cf1bd62,0x3d6dbcc4,0x3d62bcf1,0x3d55bd0e,0x3d46bd22,0x3d800000,0x3d7fbbc9,0x3d7bbc48,0x3d75bc95,
0x3d6d3cc4,0x3d753c95,0x3d7b3c48,0x3d7f3bc9,0x3d353d35,0x3d463d22,0x3d553d0e,0x3d623cf1,0x3cc43d6d,0x3cf13d62,0x3d0e3d55,0x3d223d46,0x3d80,0x3bc93d7f,0x3c483d7b,0x3c953d75,
0xbd800000,0xbbc93d7f,0x3d7b3c48,0x3c95bd75,0xbd6dbcc4,0xbcf13d62,0x3d553d0e,0x3d22bd46,0xbd35bd35,0xbd463d22,0x3d0e3d55,0x3d62bcf1,0xbcc4bd6d,0xbd753c95,0x3c483d7b,0x3d7fbbc9,
0x8000bd80,0xbd7fbbc9,0xbc483d7b,0x3d753c95,0x3cc4bd6d,0xbd62bcf1,0xbd0e3d55,0x3d463d22,0x3d35bd35,0xbd22bd46,0xbd553d0e,0x3cf13d62,0x3d6dbcc4,0xbc95bd75,0xbd7b3c48,0x3bc93d7f,
0xbcc4bd6d,0xbd7f3bc9,0xbc483d7b,0x3d623cf1,0xbd800000,0xbc953d75,0x3d553d0e,0x3d46bd22,0x3d6d3cc4,0x3d22bd46,0xbd0ebd55,0xbd753c95,0x3d35bd35,0xbcf1bd62,0xbd7b3c48,0xbbc93d7f,
0xbd6d3cc4,0x3bc93d7f,0x3d7b3c48,0x3cf1bd62,0x80003d80,0x3d753c95,0x3d0ebd55,0xbd22bd46,0x3cc4bd6d,0xbd46bd22,0xbd553d0e,0x3c953d75,0xbd35bd35,0xbd623cf1,0x3c483d7b,0x3d7f3bc9,
0x3d353d35,0x3d75bc95,0x3c48bd7b,0xbd46bd22,0xbd6d3cc4,0xbbc93d7f,0x3d553d0e,0x3d62bcf1,0xbd800000,0xbcf13d62,0x3d0e3d55,0x3d7fbbc9,0x3cc4bd6d,0xbd22bd46,0xbd7b3c48,0xbc953d75,
0xbd353d35,0x3c953d75,0x3d7b3c48,0x3d22bd46,0xbcc4bd6d,0xbd7fbbc9,0xbd0e3d55,0x3cf13d62,0x8000bd80,0xbd62bcf1,0xbd553d0e,0x3bc93d7f,0x3d6d3cc4,0x3d46bd22,0xbc48bd7b,0xbd75bc95,
0x3cc4bd6d,0xbcf1bd62,0xbd7bbc48,0xbd463d22,0xbd353d35,0x3bc93d7f,0x3d553d0e,0x3d75bc95,0x3d6dbcc4,0x3c95bd75,0xbd0ebd55,0xbd7fbbc9,0xbd800000,0xbd223d46,0x3c483d7b,0x3d623cf1,
0xbd6dbcc4,0xbd623cf1,0xbc483d7b,0x3d223d46,0x3d353d35,0x3d7fbbc9,0x3d0ebd55,0xbc95bd75,0xbcc4bd6d,0xbd75bc95,0xbd553d0e,0xbbc93d7f,0x80003d80,0x3d463d22,0x3d7bbc48,0x3cf1bd62,
0x8000bd80,0xbd22bd46,0xbd7bbc48,0xbd623cf1,0xbcc43d6d,0x3c953d75,0x3d553d0e,0x3d7fbbc9,0x3d35bd35,0x3bc9bd7f,0xbd0ebd55,0xbd75bc95,0xbd6d3cc4,0xbcf13d62,0x3c483d7b,0x3d463d22,
0xbd800000,0xbd463d22,0xbc483d7b,0x3cf13d62,0x3d6d3cc4,0x3d75bc95,0x3d0ebd55,0xbbc9bd7f,0xbd35bd35,0xbd7fbbc9,0xbd553d0e,0xbc953d75,0x3cc43d6d,0x3d623cf1,0x3d7bbc48,0x3d22bd46,
0x3d6dbcc4,0x3d22bd46,0x3c48bd7b,0xbc95bd75,0x80003d80,0x3cf13d62,0x3d553d0e,0x3d7f3bc9,0xbcc43d6d,0x3bc93d7f,0x3d0e3d55,0x3d623cf1,0xbd35bd35,0xbd75bc95,0xbd7b3c48,0xbd463d22,
0x3cc43d6d,0x3d463d22,0x3d7b3c48,0x3d75bc95,0xbd800000,0xbd623cf1,0xbd0e3d55,0xbbc93d7f,0xbd6dbcc4,0xbd7f3bc9,0xbd553d0e,0xbcf13d62,0x3d35bd35,0x3c95bd75,0xbc48bd7b,0xbd22bd46,
0xbd353d35,0xbcf13d62,0xbc483d7b,0x3bc93d7f,0x3cc43d6d,0x3d223d46,0x3d553d0e,0x3d753c95,0x8000bd80,0xbc95bd75,0xbd0ebd55,0xbd46bd22,0xbd6dbcc4,0xbd7fbbc9,0xbd7b3c48,0xbd623cf1,
0x3d353d35,0x3d623cf1,0x3d7b3c48,0x3d7fbbc9,0x3d6dbcc4,0x3d46bd22,0x3d0ebd55,0x3c95bd75,0xbd800000,0xbd753c95,0xbd553d0e,0xbd223d46,0xbcc43d6d,0xbbc93d7f,0x3c483d7b,0x3cf13d62,
0x3d6d3cc4,0x3d753c95,0x3d7b3c48,0x3d7f3bc9,0x3d353d35,0x3d463d22,0x3d553d0e,0x3d623cf1,0x3cc43d6d,0x3cf13d62,0x3d0e3d55,0x3d223d46,0x80003d80,0x3bc93d7f,0x3c483d7b,0x3c953d75,
0xbcc43d6d,0xbc953d75,0xbc483d7b,0xbbc93d7f,0xbd353d35,0xbd223d46,0xbd0e3d55,0xbcf13d62,0xbd6d3cc4,0xbd623cf1,0xbd553d0e,0xbd463d22,0xbd800000,0xbd7f3bc9,0xbd7b3c48,0xbd753c95,
0x3d80,0xbc163d7d,0xbc953d75,0xbcdb3d67,0xbd0e3d55,0xbd2c3d3e,0xbd463d22,0xbd5c3d04,0xbd6d3cc4,0xbd783c79,0xbd7f3bc9,0xbd80bb49,0xbd7bbc48,0xbd71bcac,0xbd62bcf1,0xbd4ebd18,
0xbd35bd35,0xbd18bd4e,0xbcf1bd62,0xbcacbd71,0xbc48bd7b,0xbb49bd80,0x3bc9bd7f,0x3c79bd78,0x3cc4bd6d,0x3d04bd5c,0x3d22bd46,0x3d3ebd2c,0x3d55bd0e,0x3d67bcdb,0x3d75bc95,0x3d7dbc16,
0xbd7b3c48,0xbd7dbc16,0xbd62bcf1,0xbd2cbd3e,0x3d80,0xbcac3d71,0xbd223d46,0xbd5c3d04,0x3d55bd0e,0x3d78bc79,0x3d7f3bc9,0x3d673cdb,0xbcc4bd6d,0xbb49bd80,0x3c95bd75,0x3d18bd4e,
0xbd0e3d55,0xbd4e3d18,0xbd753c95,0xbd80bb49,0x3d353d35,0x3cdb3d67,0x3bc93d7f,0xbc793d78,0x3c48bd7b,0x3d04bd5c,0x3d46bd22,0x3d71bcac,0xbd6dbcc4,0xbd3ebd2c,0xbcf1bd62,0xbc16bd7d,
0x3d6dbcc4,0x3d7d3c16,0x3d463d22,0x3cac3d71,0xbc483d7b,0xbd2c3d3e,0xbd753c95,0xbd78bc79,0x3d80,0xbd043d5c,0xbd623cf1,0xbd80bb49,0xbd55bd0e,0xbcdbbd67,0x3bc9bd7f,0x3d18bd4e,
0xbcc43d6d,0xbd4e3d18,0xbd7f3bc9,0xbd67bcdb,0xbd0ebd55,0xbb49bd80,0x3cf1bd62,0x3d5cbd04,0xbd35bd35,0xbc79bd78,0x3c95bd75,0x3d3ebd2c,0x3d7bbc48,0x3d713cac,0x3d223d46,0x3c163d7d,
0xbd0ebd55,0x3c16bd7d,0x3d46bd22,0x3d803b49,0x3cc43d6d,0xbcac3d71,0xbd623cf1,0xbd78bc79,0xbc48bd7b,0x3d04bd5c,0x3d75bc95,0x3d673cdb,0x3d80,0xbd2c3d3e,0xbd7f3bc9,0xbd4ebd18,
0xbd7bbc48,0xbd18bd4e,0x3bc9bd7f,0x3d3ebd2c,0x3d6d3cc4,0x3cdb3d67,0xbc953d75,0xbd5c3d04,0xbd55bd0e,0xbc79bd78,0x3cf1bd62,0x3d71bcac,0x3d353d35,0x3b493d80,0xbd223d46,0xbd7d3c16,
0xbd35bd35,0x3c16bd7d,0x3d62bcf1,0x3d673cdb,0x3c483d7b,0xbd2c3d3e,0xbd7fbbc9,0xbd04bd5c,0x3cc4bd6d,0x3d78bc79,0x3d463d22,0xbb493d80,0xbd553d0e,0xbd71bcac,0xbc95bd75,0x3d18bd4e,
0x3d80,0xbd4e3d18,0xbd75bc95,0xbcacbd71,0x3d0ebd55,0x3d80bb49,0x3d223d46,0xbc793d78,0xbd6d3cc4,0xbd5cbd04,0xbbc9bd7f,0x3d3ebd2c,0x3d7b3c48,0x3cdb3d67,0xbcf13d62,0xbd7d3c16,
0x3d0ebd55,0x3d7d3c16,0x3c953d75,0xbd3e3d2c,0x3d353d35,0xbcac3d71,0xbd7f3bc9,0xbd04bd5c,0xbc483d7b,0xbd783c79,0xbd22bd46,0x3cdbbd67,0xbd6dbcc4,0xbb49bd80,0x3d62bcf1,0x3d4e3d18,
0x3d7bbc48,0x3d183d4e,0xbcf13d62,0xbd80bb49,0x3d80,0xbd673cdb,0xbd46bd22,0x3c79bd78,0xbd553d0e,0xbd5cbd04,0x3bc9bd7f,0x3d71bcac,0xbcc4bd6d,0x3d2cbd3e,0x3d753c95,0x3c163d7d,
0xbcc43d6d,0xbd7dbc16,0xbbc9bd7f,0x3d71bcac,0x3d0e3d55,0xbd2c3d3e,0xbd62bcf1,0x3c79bd78,0xbd35bd35,0x3d04bd5c,0x3d753c95,0xbb493d80,0xbd7b3c48,0xbcdbbd67,0x3d46bd22,0x3d4e3d18,
0x3d6dbcc4,0x3d183d4e,0xbd223d46,0xbd67bcdb,0x3c48bd7b,0x3d80bb49,0x3c953d75,0xbd5c3d04,0x3d80,0xbd783c79,0xbcf1bd62,0x3d3ebd2c,0x3d553d0e,0xbcac3d71,0xbd7fbbc9,0xbc16bd7d,
0x3d7b3c48,0xbc163d7d,0xbd7fbbc9,0x3b49bd80,0x3d6d3cc4,0xbcac3d71,0xbd75bc95,0x3c79bd78,0x3d553d0e,0xbd043d5c,0xbd62bcf1,0x3cdbbd67,0x3d353d35,0xbd2c3d3e,0xbd46bd22,0x3d18bd4e,
0x3d0e3d55,0xbd4e3d18,0xbd22bd46,0x3d3ebd2c,0x3cc43d6d,0xbd673cdb,0xbcf1bd62,0x3d5cbd04,0x3c483d7b,0xbd783c79,0xbc95bd75,0x3d71bcac,0x3d80,0xbd803b49,0xbbc9bd7f,0x3d7dbc16,
0xbd800000,0xbd7dbc16,0xbd75bc95,0xbd67bcdb,0xbd55bd0e,0xbd3ebd2c,0xbd22bd46,0xbd04bd5c,0xbcc4bd6d,0xbc79bd78,0xbbc9bd7f,0x3b49bd80,0x3c48bd7b,0x3cacbd71,0x3cf1bd62,0x3d18bd4e,
0x3d35bd35,0x3d4ebd18,0x3d62bcf1,0x3d71bcac,0x3d7bbc48,0x3d80bb49,0x3d7f3bc9,0x3d783c79,0x3d6d3cc4,0x3d5c3d04,0x3d463d22,0x3d2c3d3e,0x3d0e3d55,0x3cdb3d67,0x3c953d75,0x3c163d7d,
0xbc48bd7b,0x3c16bd7d,0x3cf1bd62,0x3d3ebd2c,0xbd800000,0xbd71bcac,0xbd46bd22,0xbd04bd5c,0x3d0e3d55,0x3c793d78,0xbbc93d7f,0xbcdb3d67,0x3d6dbcc4,0x3d80bb49,0x3d753c95,0x3d4e3d18,
0xbd55bd0e,0xbd18bd4e,0xbc95bd75,0x3b49bd80,0xbd353d35,0xbd673cdb,0xbd7f3bc9,0xbd78bc79,0x3d7b3c48,0x3d5c3d04,0x3d223d46,0x3cac3d71,0x3cc4bd6d,0x3d2cbd3e,0x3d62bcf1,0x3d7dbc16,
0x3cc43d6d,0xbc163d7d,0xbd223d46,0xbd713cac,0xbd7bbc48,0xbd3ebd2c,0xbc95bd75,0x3c79bd78,0xbd800000,0xbd5cbd04,0xbcf1bd62,0x3b49bd80,0x3d0ebd55,0x3d67bcdb,0x3d7f3bc9,0x3d4e3d18,
0xbd6dbcc4,0xbd18bd4e,0xbbc9bd7f,0x3cdbbd67,0x3d55bd0e,0x3d80bb49,0x3d623cf1,0x3d043d5c,0x3d35bd35,0x3d78bc79,0x3d753c95,0x3d2c3d3e,0x3c483d7b,0xbcac3d71,0xbd463d22,0xbd7d3c16,
0x3d55bd0e,0x3d7d3c16,0x3d223d46,0xbb493d80,0xbd6d3cc4,0xbd71bcac,0xbcf1bd62,0x3c79bd78,0x3d7bbc48,0x3d5c3d04,0x3c953d75,0xbcdb3d67,0xbd800000,0xbd3ebd2c,0xbbc9bd7f,0x3d18bd4e,
0x3c48bd7b,0x3d4ebd18,0x3d7f3bc9,0x3d2c3d3e,0xbcc43d6d,0xbd673cdb,0xbd75bc95,0xbd04bd5c,0x3d0ebd55,0x3d78bc79,0x3d623cf1,0x3cac3d71,0xbd353d35,0xbd803b49,0xbd46bd22,0xbc16bd7d,
0x3d35bd35,0x3d7d3c16,0x3cf13d62,0xbcdb3d67,0xbd7b3c48,0xbd3ebd2c,0x3bc9bd7f,0x3d5cbd04,0x3d6d3cc4,0x3c793d78,0xbd223d46,0xbd80bb49,0xbd0ebd55,0x3cacbd71,0x3d75bc95,0x3d4e3d18,
0xbd800000,0xbd18bd4e,0x3c95bd75,0x3d71bcac,0x3d553d0e,0x3b493d80,0xbd463d22,0xbd78bc79,0xbcc4bd6d,0x3d04bd5c,0x3d7fbbc9,0x3d2c3d3e,0xbc483d7b,0xbd673cdb,0xbd62bcf1,0xbc16bd7d,
0x3d553d0e,0xbc163d7d,0xbd753c95,0xbd2cbd3e,0xbd353d35,0xbd71bcac,0xbbc9bd7f,0x3d5cbd04,0xbd7bbc48,0xbc79bd78,0x3d46bd22,0x3d673cdb,0x3cc4bd6d,0x3d80bb49,0x3cf13d62,0xbd183d4e,
0x3c483d7b,0xbd4e3d18,0xbd62bcf1,0x3b49bd80,0xbd800000,0xbcdbbd67,0x3d22bd46,0x3d783c79,0xbd0ebd55,0x3d04bd5c,0x3d7f3bc9,0x3cac3d71,0x3d6dbcc4,0x3d3e3d2c,0xbc953d75,0xbd7d3c16,
0xbd6dbcc4,0x3c16bd7d,0x3d7fbbc9,0x3cac3d71,0xbd553d0e,0xbd3ebd2c,0x3cf1bd62,0x3d783c79,0x3d35bd35,0x3d5c3d04,0xbc953d75,0xbd80bb49,0xbc48bd7b,0x3d67bcdb,0x3d223d46,0xbd183d4e,
0x3cc43d6d,0xbd4e3d18,0xbd46bd22,0x3cdbbd67,0x3d7b3c48,0x3b493d80,0xbd753c95,0xbd04bd5c,0xbd800000,0xbc79bd78,0x3d62bcf1,0x3d2c3d3e,0xbd0e3d55,0xbd71bcac,0x3bc9bd7f,0x3d7dbc16,
0xbc483d7b,0xbd7dbc16,0x3bc9bd7f,0x3d803b49,0xbcc43d6d,0xbd71bcac,0x3c95bd75,0x3d783c79,0xbd0e3d55,0xbd5cbd04,0x3cf1bd62,0x3d673cdb,0xbd353d35,0xbd3ebd2c,0x3d22bd46,0x3d4e3d18,
0xbd553d0e,0xbd18bd4e,0x3d46bd22,0x3d2c3d3e,0xbd6d3cc4,0xbcdbbd67,0x3d62bcf1,0x3d043d5c,0xbd7b3c48,0xbc79bd78,0x3d75bc95,0x3cac3d71,0xbd800000,0xbb49bd80,0x3d7fbbc9,0x3c163d7d,
0x3d80,0xbd7dbc16,0x3c95bd75,0x3d673cdb,0xbd0e3d55,0xbd3ebd2c,0x3d46bd22,0x3d043d5c,0xbd6d3cc4,0xbc79bd78,0x3d7fbbc9,0xbb493d80,0xbd7bbc48,0x3cacbd71,0x3d623cf1,0xbd183d4e,
0xbd35bd35,0x3d4ebd18,0x3cf13d62,0xbd713cac,0xbc48bd7b,0x3d80bb49,0xbbc93d7f,0xbd78bc79,0x3cc4bd6d,0x3d5c3d04,0xbd223d46,0xbd2cbd3e,0x3d55bd0e,0x3cdb3d67,0xbd753c95,0xbc16bd7d,
0xbd7b3c48,0x3c16bd7d,0x3d623cf1,0xbd3e3d2c,0x3d80,0xbd71bcac,0x3d22bd46,0x3d043d5c,0x3d55bd0e,0x3c793d78,0xbd7fbbc9,0x3cdbbd67,0xbcc4bd6d,0x3d80bb49,0xbc953d75,0xbd4ebd18,
0xbd0e3d55,0xbd18bd4e,0x3d75bc95,0xbb493d80,0x3d353d35,0xbd673cdb,0xbbc9bd7f,0x3d783c79,0x3c48bd7b,0x3d5c3d04,0xbd463d22,0xbcacbd71,0xbd6dbcc4,0x3d2cbd3e,0x3cf13d62,0xbd7d3c16,
0x3d6dbcc4,0xbc163d7d,0xbd46bd22,0x3d71bcac,0xbc483d7b,0xbd3ebd2c,0x3d75bc95,0xbc793d78,0x3d80,0xbd5cbd04,0x3d62bcf1,0xbb493d80,0xbd55bd0e,0x3d67bcdb,0xbbc93d7f,0xbd4ebd18,
0xbcc43d6d,0xbd18bd4e,0x3d7fbbc9,0xbcdb3d67,0xbd0ebd55,0x3d80bb49,0xbcf13d62,0xbd04bd5c,0xbd35bd35,0x3d78bc79,0xbc953d75,0xbd2cbd3e,0x3d7bbc48,0xbcac3d71,0xbd22bd46,0x3d7dbc16,
0xbd0ebd55,0x3d7d3c16,0xbd463d22,0x3b49bd80,0x3cc43d6d,0xbd71bcac,0x3d62bcf1,0xbc793d78,0xbc48bd7b,0x3d5c3d04,0xbd753c95,0x3cdbbd67,0x3d80,0xbd3ebd2c,0x3d7fbbc9,0xbd183d4e,
0xbd7bbc48,0x3d4ebd18,0xbbc93d7f,0xbd2cbd3e,0x3d6d3cc4,0xbd673cdb,0x3c95bd75,0x3d043d5c,0xbd55bd0e,0x3d78bc79,0xbcf13d62,0xbcacbd71,0x3d353d35,0xbd803b49,0x3d22bd46,0x3c163d7d,
0xbd35bd35,0x3d7d3c16,0xbd623cf1,0x3cdbbd67,0x3c483d7b,0xbd3ebd2c,0x3d7f3bc9,0xbd5c3d04,0x3cc4bd6d,0x3c793d78,0xbd46bd22,0x3d803b49,0xbd553d0e,0x3cacbd71,0x3c953d75,0xbd4ebd18,
0x3d80,0xbd18bd4e,0x3d753c95,0xbd713cac,0x3d0ebd55,0x3b493d80,0xbd22bd46,0x3d783c79,0xbd6d3cc4,0x3d04bd5c,0x3bc93d7f,0xbd2cbd3e,0x3d7b3c48,0xbd673cdb,0x3cf1bd62,0x3c163d7d,
0x3d0ebd55,0xbc163d7d,0xbc95bd75,0x3d2c3d3e,0x3d353d35,0xbd71bcac,0x3d7fbbc9,0xbd5c3d04,0xbc483d7b,0xbc79bd78,0x3d223d46,0xbd67bcdb,0xbd6dbcc4,0x3d80bb49,0xbd623cf1,0x3d18bd4e,
0x3d7bbc48,0xbd4e3d18,0x3cf1bd62,0xbb493d80,0x3d80,0xbcdbbd67,0x3d463d22,0xbd78bc79,0xbd553d0e,0x3d04bd5c,0xbbc93d7f,0xbcacbd71,0xbcc4bd6d,0x3d3e3d2c,0xbd75bc95,0x3d7dbc16,
0xbcc43d6d,0x3c16bd7d,0x3bc93d7f,0xbcacbd71,0x3d0e3d55,0xbd3ebd2c,0x3d623cf1,0xbd78bc79,0xbd35bd35,0x3d5c3d04,0xbd75bc95,0x3d803b49,0xbd7b3c48,0x3d67bcdb,0xbd463d22,0x3d18bd4e,
0x3d6dbcc4,0xbd4e3d18,0x3d22bd46,0xbcdb3d67,0x3c48bd7b,0x3b493d80,0xbc95bd75,0x3d043d5c,0x3d80,0xbc79bd78,0x3cf13d62,0xbd2cbd3e,0x3d553d0e,0xbd71bcac,0x3d7f3bc9,0xbd7d3c16,
0x3d7b3c48,0xbd7dbc16,0x3d7f3bc9,0xbd80bb49,0x3d6d3cc4,0xbd71bcac,0x3d753c95,0xbd78bc79,0x3d553d0e,0xbd5cbd04,0x3d623cf1,0xbd67bcdb,0x3d353d35,0xbd3ebd2c,0x3d463d22,0xbd4ebd18,
0x3d0e3d55,0xbd18bd4e,0x3d223d46,0xbd2cbd3e,0x3cc43d6d,0xbcdbbd67,0x3cf13d62,0xbd04bd5c,0x3c483d7b,0xbc79bd78,0x3c953d75,0xbcacbd71,0x3d80,0xbb49bd80,0x3bc93d7f,0xbc16bd7d,
0xbd800000,0x3c16bd7d,0x3d753c95,0xbcdb3d67,0xbd55bd0e,0x3d2cbd3e,0x3d223d46,0xbd5c3d04,0xbcc4bd6d,0x3d78bc79,0x3bc93d7f,0xbd80bb49,0x3c48bd7b,0x3d713cac,0xbcf13d62,0xbd4ebd18,
0x3d35bd35,0x3d183d4e,0xbd623cf1,0xbcacbd71,0x3d7bbc48,0x3b493d80,0xbd7fbbc9,0x3c79bd78,0x3d6d3cc4,0xbd043d5c,0xbd46bd22,0x3d3ebd2c,0x3d0e3d55,0xbd673cdb,0xbc95bd75,0x3d7dbc16,
0xbc48bd7b,0x3d7d3c16,0xbcf13d62,0xbd2cbd3e,0xbd800000,0x3cacbd71,0x3d463d22,0xbd5c3d04,0x3d0e3d55,0xbd783c79,0x3bc9bd7f,0x3d673cdb,0x3d6dbcc4,0x3b493d80,0xbd75bc95,0x3d18bd4e,
0xbd55bd0e,0x3d4ebd18,0x3c953d75,0xbd80bb49,0xbd353d35,0xbcdbbd67,0x3d7fbbc9,0xbc793d78,0x3d7b3c48,0xbd043d5c,0xbd22bd46,0x3d71bcac,0x3cc4bd6d,0x3d3e3d2c,0xbd623cf1,0xbc16bd7d,
0x3cc43d6d,0xbd7dbc16,0x3d22bd46,0x3cac3d71,0xbd7bbc48,0x3d2cbd3e,0x3c953d75,0xbd78bc79,0xbd800000,0x3d04bd5c,0x3cf13d62,0xbd80bb49,0x3d0ebd55,0x3cdb3d67,0xbd7fbbc9,0x3d18bd4e,
0xbd6dbcc4,0x3d4ebd18,0x3bc93d7f,0xbd67bcdb,0x3d55bd0e,0x3b493d80,0xbd62bcf1,0x3d5cbd04,0x3d35bd35,0x3c793d78,0xbd75bc95,0x3d3ebd2c,0x3c483d7b,0xbd71bcac,0x3d46bd22,0x3c163d7d,
0x3d55bd0e,0xbc163d7d,0xbd22bd46,0x3d803b49,0xbd6d3cc4,0x3cacbd71,0x3cf13d62,0xbd78bc79,0x3d7bbc48,0xbd043d5c,0xbc95bd75,0x3d673cdb,0xbd800000,0x3d2cbd3e,0x3bc93d7f,0xbd4ebd18,
0x3c48bd7b,0x3d183d4e,0xbd7fbbc9,0x3d3ebd2c,0xbcc43d6d,0xbcdbbd67,0x3d753c95,0xbd5c3d04,0x3d0ebd55,0x3c793d78,0xbd62bcf1,0x3d71bcac,0xbd353d35,0xbb49bd80,0x3d463d22,0xbd7d3c16,
0x3d35bd35,0xbc163d7d,0xbcf1bd62,0x3d673cdb,0xbd7b3c48,0x3d2cbd3e,0xbbc93d7f,0xbd04bd5c,0x3d6d3cc4,0xbd783c79,0x3d22bd46,0xbb493d80,0xbd0ebd55,0x3d713cac,0xbd753c95,0x3d18bd4e,
0xbd800000,0x3d4ebd18,0xbc953d75,0xbcacbd71,0x3d553d0e,0xbd803b49,0x3d46bd22,0xbc793d78,0xbcc4bd6d,0x3d5c3d04,0xbd7f3bc9,0x3d3ebd2c,0xbc483d7b,0xbcdbbd67,0x3d623cf1,0xbd7d3c16,
0x3d553d0e,0xbd7dbc16,0x3d75bc95,0xbd3e3d2c,0xbd353d35,0x3cacbd71,0x3bc93d7f,0xbd04bd5c,0xbd7bbc48,0x3d78bc79,0xbd463d22,0x3cdbbd67,0x3cc4bd6d,0x3b493d80,0xbcf1bd62,0x3d4e3d18,
0x3c483d7b,0xbd18bd4e,0x3d623cf1,0xbd80bb49,0xbd800000,0x3d67bcdb,0xbd223d46,0x3c79bd78,0xbd0ebd55,0x3d5c3d04,0xbd7fbbc9,0x3d71bcac,0x3d6dbcc4,0xbd2c3d3e,0x3c95bd75,0x3c163d7d,
0xbd6dbcc4,0x3d7d3c16,0xbd7f3bc9,0x3d71bcac,0xbd553d0e,0x3d2cbd3e,0xbcf13d62,0x3c79bd78,0x3d35bd35,0xbd043d5c,0x3c95bd75,0xbb493d80,0xbc48bd7b,0x3cdb3d67,0xbd22bd46,0x3d4e3d18,
0x3cc43d6d,0xbd18bd4e,0x3d463d22,0xbd67bcdb,0x3d7b3c48,0xbd803b49,0x3d75bc95,0xbd5c3d04,0xbd800000,0x3d78bc79,0xbd623cf1,0x3d3ebd2c,0xbd0e3d55,0x3cacbd71,0xbbc93d7f,0xbc16bd7d,
0xbc483d7b,0x3c16bd7d,0xbbc93d7f,0x3b49bd80,0xbcc43d6d,0x3cacbd71,0xbc953d75,0x3c79bd78,0xbd0e3d55,0x3d04bd5c,0xbcf13d62,0x3cdbbd67,0xbd353d35,0x3d2cbd3e,0xbd223d46,0x3d18bd4e,
0xbd553d0e,0x3d4ebd18,0xbd463d22,0x3d3ebd2c,0xbd6d3cc4,0x3d67bcdb,0xbd623cf1,0x3d5cbd04,0xbd7b3c48,0x3d78bc79,0xbd753c95,0x3d71bcac,0xbd800000,0x3d80bb49,0xbd7f3bc9,0x3d7dbc16,
0x3d80,0x3c16bd7d,0xbc953d75,0x3cdbbd67,0xbd0e3d55,0x3d2cbd3e,0xbd463d22,0x3d5cbd04,0xbd6d3cc4,0x3d78bc79,0xbd7f3bc9,0x3d803b49,0xbd7bbc48,0x3d713cac,0xbd62bcf1,0x3d4e3d18,
0xbd35bd35,0x3d183d4e,0xbcf1bd62,0x3cac3d71,0xbc48bd7b,0x3b493d80,0x3bc9bd7f,0xbc793d78,0x3cc4bd6d,0xbd043d5c,0x3d22bd46,0xbd3e3d2c,0x3d55bd0e,0xbd673cdb,0x3d75bc95,0xbd7d3c16,
0xbd7b3c48,0x3d7d3c16,0xbd62bcf1,0x3d2c3d3e,0x3d80,0x3cacbd71,0xbd223d46,0x3d5cbd04,0x3d55bd0e,0xbd783c79,0x3d7f3bc9,0xbd67bcdb,0xbcc4bd6d,0x3b493d80,0x3c95bd75,0xbd183d4e,
0xbd0e3d55,0x3d4ebd18,0xbd753c95,0x3d803b49,0x3d353d35,0xbcdbbd67,0x3bc93d7f,0x3c79bd78,0x3c48bd7b,0xbd043d5c,0x3d46bd22,0xbd713cac,0xbd6dbcc4,0x3d3e3d2c,0xbcf1bd62,0x3c163d7d,
0x3d6dbcc4,0xbd7dbc16,0x3d463d22,0xbcacbd71,0xbc483d7b,0x3d2cbd3e,0xbd753c95,0x3d783c79,0x3d80,0x3d04bd5c,0xbd623cf1,0x3d803b49,0xbd55bd0e,0x3cdb3d67,0x3bc9bd7f,0xbd183d4e,
0xbcc43d6d,0x3d4ebd18,0xbd7f3bc9,0x3d673cdb,0xbd0ebd55,0x3b493d80,0x3cf1bd62,0xbd5c3d04,0xbd35bd35,0x3c793d78,0x3c95bd75,0xbd3e3d2c,0x3d7bbc48,0xbd71bcac,0x3d223d46,0xbc16bd7d,
0xbd0ebd55,0xbc163d7d,0x3d46bd22,0xbd80bb49,0x3cc43d6d,0x3cacbd71,0xbd623cf1,0x3d783c79,0xbc48bd7b,0xbd043d5c,0x3d75bc95,0xbd67bcdb,0x3d80,0x3d2cbd3e,0xbd7f3bc9,0x3d4e3d18,
0xbd7bbc48,0x3d183d4e,0x3bc9bd7f,0xbd3e3d2c,0x3d6d3cc4,0xbcdbbd67,0xbc953d75,0x3d5cbd04,0xbd55bd0e,0x3c793d78,0x3cf1bd62,0xbd713cac,0x3d353d35,0xbb49bd80,0xbd223d46,0x3d7dbc16,
0xbd35bd35,0xbc163d7d,0x3d62bcf1,0xbd67bcdb,0x3c483d7b,0x3d2cbd3e,0xbd7fbbc9,0x3d043d5c,0x3cc4bd6d,0xbd783c79,0x3d463d22,0x3b49bd80,0xbd553d0e,0x3d713cac,0xbc95bd75,0xbd183d4e,
0x3d80,0x3d4ebd18,0xbd75bc95,0x3cac3d71,0x3d0ebd55,0xbd803b49,0x3d223d46,0x3c79bd78,0xbd6d3cc4,0x3d5c3d04,0xbbc9bd7f,0xbd3e3d2c,0x3d7b3c48,0xbcdbbd67,0xbcf13d62,0x3d7dbc16,
0x3d0ebd55,0xbd7dbc16,0x3c953d75,0x3d3ebd2c,0x3d353d35,0x3cacbd71,0xbd7f3bc9,0x3d043d5c,0xbc483d7b,0x3d78bc79,0xbd22bd46,0xbcdb3d67,0xbd6dbcc4,0x3b493d80,0x3d62bcf1,0xbd4ebd18,
0x3d7bbc48,0xbd18bd4e,0xbcf13d62,0x3d803b49,0x3d80,0x3d67bcdb,0xbd46bd22,0xbc793d78,0xbd553d0e,0x3d5c3d04,0x3bc9bd7f,0xbd713cac,0xbcc4bd6d,0xbd2c3d3e,0x3d753c95,0xbc16bd7d,
0xbcc43d6d,0x3d7d3c16,0xbbc9bd7f,0xbd713cac,0x3d0e3d55,0x3d2cbd3e,0xbd62bcf1,0xbc793d78,0xbd35bd35,0xbd043d5c,0x3d753c95,0x3b49bd80,0xbd7b3c48,0x3cdb3d67,0x3d46bd22,0xbd4ebd18,
0x3d6dbcc4,0xbd18bd4e,0xbd223d46,0x3d673cdb,0x3c48bd7b,0xbd803b49,0x3c953d75,0x3d5cbd04,0x3d80,0x3d78bc79,0xbcf1bd62,0xbd3e3d2c,0x3d553d0e,0x3cacbd71,0xbd7fbbc9,0x3c163d7d,
0x3d7b3c48,0x3c16bd7d,0xbd7fbbc9,0xbb493d80,0x3d6d3cc4,0x3cacbd71,0xbd75bc95,0xbc793d78,0x3d553d0e,0x3d04bd5c,0xbd62bcf1,0xbcdb3d67,0x3d353d35,0x3d2cbd3e,0xbd46bd22,0xbd183d4e,
0x3d0e3d55,0x3d4ebd18,0xbd22bd46,0xbd3e3d2c,0x3cc43d6d,0x3d67bcdb,0xbcf1bd62,0xbd5c3d04,0x3c483d7b,0x3d78bc79,0xbc95bd75,0xbd713cac,0x3d80,0x3d80bb49,0xbbc9bd7f,0xbd7d3c16,
0xbd800000,0x3d7d3c16,0xbd75bc95,0x3d673cdb,0xbd55bd0e,0x3d3e3d2c,0xbd22bd46,0x3d043d5c,0xbcc4bd6d,0x3c793d78,0xbbc9bd7f,0xbb493d80,0x3c48bd7b,0xbcac3d71,0x3cf1bd62,0xbd183d4e,
0x3d35bd35,0xbd4e3d18,0x3d62bcf1,0xbd713cac,0x3d7bbc48,0xbd803b49,0x3d7f3bc9,0xbd78bc79,0x3d6d3cc4,0xbd5cbd04,0x3d463d22,0xbd2cbd3e,0x3d0e3d55,0xbcdbbd67,0x3c953d75,0xbc16bd7d,
0xbc48bd7b,0xbc163d7d,0x3cf1bd62,0xbd3e3d2c,0xbd800000,0x3d713cac,0xbd46bd22,0x3d043d5c,0x3d0e3d55,0xbc79bd78,0xbbc93d7f,0x3cdbbd67,0x3d6dbcc4,0xbd803b49,0x3d753c95,0xbd4ebd18,
0xbd55bd0e,0x3d183d4e,0xbc95bd75,0xbb493d80,0xbd353d35,0x3d67bcdb,0xbd7f3bc9,0x3d783c79,0x3d7b3c48,0xbd5cbd04,0x3d223d46,0xbcacbd71,0x3cc4bd6d,0xbd2c3d3e,0x3d62bcf1,0xbd7d3c16,
0x3cc43d6d,0x3c16bd7d,0xbd223d46,0x3d71bcac,0xbd7bbc48,0x3d3e3d2c,0xbc95bd75,0xbc793d78,0xbd800000,0x3d5c3d04,0xbcf1bd62,0xbb493d80,0x3d0ebd55,0xbd673cdb,0x3d7f3bc9,0xbd4ebd18,
0xbd6dbcc4,0x3d183d4e,0xbbc9bd7f,0xbcdb3d67,0x3d55bd0e,0xbd803b49,0x3d623cf1,0xbd04bd5c,0x3d35bd35,0xbd783c79,0x3d753c95,0xbd2cbd3e,0x3c483d7b,0x3cacbd71,0xbd463d22,0x3d7dbc16,
0x3d55bd0e,0xbd7dbc16,0x3d223d46,0x3b49bd80,0xbd6d3cc4,0x3d713cac,0xbcf1bd62,0xbc793d78,0x3d7bbc48,0xbd5cbd04,0x3c953d75,0x3cdbbd67,0xbd800000,0x3d3e3d2c,0xbbc9bd7f,0xbd183d4e,
0x3c48bd7b,0xbd4e3d18,0x3d7f3bc9,0xbd2cbd3e,0xbcc43d6d,0x3d67bcdb,0xbd75bc95,0x3d043d5c,0x3d0ebd55,0xbd783c79,0x3d623cf1,0xbcacbd71,0xbd353d35,0x3d80bb49,0xbd46bd22,0x3c163d7d,
0x3d35bd35,0xbd7dbc16,0x3cf13d62,0x3cdbbd67,0xbd7b3c48,0x3d3e3d2c,0x3bc9bd7f,0xbd5c3d04,0x3d6d3cc4,0xbc79bd78,0xbd223d46,0x3d803b49,0xbd0ebd55,0xbcac3d71,0x3d75bc95,0xbd4ebd18,
0xbd800000,0x3d183d4e,0x3c95bd75,0xbd713cac,0x3d553d0e,0xbb49bd80,0xbd463d22,0x3d783c79,0xbcc4bd6d,0xbd043d5c,0x3d7fbbc9,0xbd2cbd3e,0xbc483d7b,0x3d67bcdb,0xbd62bcf1,0x3c163d7d,
0x3d553d0e,0x3c16bd7d,0xbd753c95,0x3d2c3d3e,0xbd353d35,0x3d713cac,0xbbc9bd7f,0xbd5c3d04,0xbd7bbc48,0x3c793d78,0x3d46bd22,0xbd67bcdb,0x3cc4bd6d,0xbd803b49,0x3cf13d62,0x3d18bd4e,
0x3c483d7b,0x3d4ebd18,0xbd62bcf1,0xbb493d80,0xbd800000,0x3cdb3d67,0x3d22bd46,0xbd78bc79,0xbd0ebd55,0xbd043d5c,0x3d7f3bc9,0xbcacbd71,0x3d6dbcc4,0xbd3ebd2c,0xbc953d75,0x3d7dbc16,
0xbd6dbcc4,0xbc163d7d,0x3d7fbbc9,0xbcacbd71,0xbd553d0e,0x3d3e3d2c,0x3cf1bd62,0xbd78bc79,0x3d35bd35,0xbd5cbd04,0xbc953d75,0x3d803b49,0xbc48bd7b,0xbd673cdb,0x3d223d46,0x3d18bd4e,
0x3cc43d6d,0x3d4ebd18,0xbd46bd22,0xbcdb3d67,0x3d7b3c48,0xbb49bd80,0xbd753c95,0x3d043d5c,0xbd800000,0x3c793d78,0x3d62bcf1,0xbd2cbd3e,0xbd0e3d55,0x3d713cac,0x3bc9bd7f,0xbd7d3c16,
0xbc483d7b,0x3d7d3c16,0x3bc9bd7f,0xbd80bb49,0xbcc43d6d,0x3d713cac,0x3c95bd75,0xbd78bc79,0xbd0e3d55,0x3d5c3d04,0x3cf1bd62,0xbd67bcdb,0xbd353d35,0x3d3e3d2c,0x3d22bd46,0xbd4ebd18,
0xbd553d0e,0x3d183d4e,0x3d46bd22,0xbd2cbd3e,0xbd6d3cc4,0x3cdb3d67,0x3d62bcf1,0xbd04bd5c,0xbd7b3c48,0x3c793d78,0x3d75bc95,0xbcacbd71,0xbd800000,0x3b493d80,0x3d7fbbc9,0xbc16bd7d,
0x3d80,0x3d7d3c16,0x3c95bd75,0xbd67bcdb,0xbd0e3d55,0x3d3e3d2c,0x3d46bd22,0xbd04bd5c,0xbd6d3cc4,0x3c793d78,0x3d7fbbc9,0x3b49bd80,0xbd7bbc48,0xbcac3d71,0x3d623cf1,0x3d18bd4e,
0xbd35bd35,0xbd4e3d18,0x3cf13d62,0x3d71bcac,0xbc48bd7b,0xbd803b49,0xbbc93d7f,0x3d783c79,0x3cc4bd6d,0xbd5cbd04,0xbd223d46,0x3d2c3d3e,0x3d55bd0e,0xbcdbbd67,0xbd753c95,0x3c163d7d,
0xbd7b3c48,0xbc163d7d,0x3d623cf1,0x3d3ebd2c,0x3d80,0x3d713cac,0x3d22bd46,0xbd04bd5c,0x3d55bd0e,0xbc79bd78,0xbd7fbbc9,0xbcdb3d67,0xbcc4bd6d,0xbd803b49,0xbc953d75,0x3d4e3d18,
0xbd0e3d55,0x3d183d4e,0x3d75bc95,0x3b49bd80,0x3d353d35,0x3d67bcdb,0xbbc9bd7f,0xbd78bc79,0x3c48bd7b,0xbd5cbd04,0xbd463d22,0x3cac3d71,0xbd6dbcc4,0xbd2c3d3e,0x3cf13d62,0x3d7dbc16,
0x3d6dbcc4,0x3c16bd7d,0xbd46bd22,0xbd713cac,0xbc483d7b,0x3d3e3d2c,0x3d75bc95,0x3c79bd78,0x3d80,0x3d5c3d04,0x3d62bcf1,0x3b49bd80,0xbd55bd0e,0xbd673cdb,0xbbc93d7f,0x3d4e3d18,
0xbcc43d6d,0x3d183d4e,0x3d7fbbc9,0x3cdbbd67,0xbd0ebd55,0xbd803b49,0xbcf13d62,0x3d043d5c,0xbd35bd35,0xbd783c79,0xbc953d75,0x3d2c3d3e,0x3d7bbc48,0x3cacbd71,0xbd22bd46,0xbd7d3c16,
0xbd0ebd55,0xbd7dbc16,0xbd463d22,0xbb493d80,0x3cc43d6d,0x3d713cac,0x3d62bcf1,0x3c79bd78,0xbc48bd7b,0xbd5cbd04,0xbd753c95,0xbcdb3d67,0x3d80,0x3d3e3d2c,0x3d7fbbc9,0x3d18bd4e,
0xbd7bbc48,0xbd4e3d18,0xbbc93d7f,0x3d2c3d3e,0x3d6d3cc4,0x3d67bcdb,0x3c95bd75,0xbd04bd5c,0xbd55bd0e,0xbd783c79,0xbcf13d62,0x3cac3d71,0x3d353d35,0x3d80bb49,0x3d22bd46,0xbc16bd7d,
0xbd35bd35,0xbd7dbc16,0xbd623cf1,0xbcdb3d67,0x3c483d7b,0x3d3e3d2c,0x3d7f3bc9,0x3d5cbd04,0x3cc4bd6d,0xbc79bd78,0xbd46bd22,0xbd80bb49,0xbd553d0e,0xbcac3d71,0x3c953d75,0x3d4e3d18,
0x3d80,0x3d183d4e,0x3d753c95,0x3d71bcac,0x3d0ebd55,0xbb49bd80,0xbd22bd46,0xbd78bc79,0xbd6d3cc4,0xbd043d5c,0x3bc93d7f,0x3d2c3d3e,0x3d7b3c48,0x3d67bcdb,0x3cf1bd62,0xbc16bd7d,
0x3d0ebd55,0x3c16bd7d,0xbc95bd75,0xbd2cbd3e,0x3d353d35,0x3d713cac,0x3d7fbbc9,0x3d5cbd04,0xbc483d7b,0x3c793d78,0x3d223d46,0x3d673cdb,0xbd6dbcc4,0xbd803b49,0xbd623cf1,0xbd183d4e,
0x3d7bbc48,0x3d4ebd18,0x3cf1bd62,0x3b49bd80,0x3d80,0x3cdb3d67,0x3d463d22,0x3d783c79,0xbd553d0e,0xbd043d5c,0xbbc93d7f,0x3cac3d71,0xbcc4bd6d,0xbd3ebd2c,0xbd75bc95,0xbd7d3c16,
0xbcc43d6d,0xbc163d7d,0x3bc93d7f,0x3cac3d71,0x3d0e3d55,0x3d3e3d2c,0x3d623cf1,0x3d783c79,0xbd35bd35,0xbd5cbd04,0xbd75bc95,0xbd80bb49,0xbd7b3c48,0xbd673cdb,0xbd463d22,0xbd183d4e,
0x3d6dbcc4,0x3d4ebd18,0x3d22bd46,0x3cdbbd67,0x3c48bd7b,0xbb49bd80,0xbc95bd75,0xbd04bd5c,0x3d80,0x3c793d78,0x3cf13d62,0x3d2c3d3e,0x3d553d0e,0x3d713cac,0x3d7f3bc9,0x3d7dbc16,
0x3d7b3c48,0x3d7d3c16,0x3d7f3bc9,0x3d803b49,0x3d6d3cc4,0x3d713cac,0x3d753c95,0x3d783c79,0x3d553d0e,0x3d5c3d04,0x3d623cf1,0x3d673cdb,0x3d353d35,0x3d3e3d2c,0x3d463d22,0x3d4e3d18,
0x3d0e3d55,0x3d183d4e,0x3d223d46,0x3d2c3d3e,0x3cc43d6d,0x3cdb3d67,0x3cf13d62,0x3d043d5c,0x3c483d7b,0x3c793d78,0x3c953d75,0x3cac3d71,0x3d80,0x3b493d80,0x3bc93d7f,0x3c163d7d,
0xbd800000,0xbc163d7d,0x3d753c95,0x3cdbbd67,0xbd55bd0e,0xbd2c3d3e,0x3d223d46,0x3d5cbd04,0xbcc4bd6d,0xbd783c79,0x3bc93d7f,0x3d803b49,0x3c48bd7b,0xbd71bcac,0xbcf13d62,0x3d4e3d18,
0x3d35bd35,0xbd18bd4e,0xbd623cf1,0x3cac3d71,0x3d7bbc48,0xbb49bd80,0xbd7fbbc9,0xbc793d78,0x3d6d3cc4,0x3d04bd5c,0xbd46bd22,0xbd3e3d2c,0x3d0e3d55,0x3d67bcdb,0xbc95bd75,0xbd7d3c16,
0xbc48bd7b,0xbd7dbc16,0xbcf13d62,0x3d2c3d3e,0xbd800000,0xbcac3d71,0x3d463d22,0x3d5cbd04,0x3d0e3d55,0x3d78bc79,0x3bc9bd7f,0xbd67bcdb,0x3d6dbcc4,0xbb49bd80,0xbd75bc95,0xbd183d4e,
0xbd55bd0e,0xbd4e3d18,0x3c953d75,0x3d803b49,0xbd353d35,0x3cdb3d67,0x3d7fbbc9,0x3c79bd78,0x3d7b3c48,0x3d04bd5c,0xbd22bd46,0xbd713cac,0x3cc4bd6d,0xbd3ebd2c,0xbd623cf1,0x3c163d7d,
0x3cc43d6d,0x3d7d3c16,0x3d22bd46,0xbcacbd71,0xbd7bbc48,0xbd2c3d3e,0x3c953d75,0x3d783c79,0xbd800000,0xbd043d5c,0x3cf13d62,0x3d803b49,0x3d0ebd55,0xbcdbbd67,0xbd7fbbc9,0xbd183d4e,
0xbd6dbcc4,0xbd4e3d18,0x3bc93d7f,0x3d673cdb,0x3d55bd0e,0xbb49bd80,0xbd62bcf1,0xbd5c3d04,0x3d35bd35,0xbc79bd78,0xbd75bc95,0xbd3e3d2c,0x3c483d7b,0x3d713cac,0x3d46bd22,0xbc16bd7d,
0x3d55bd0e,0x3c16bd7d,0xbd22bd46,0xbd80bb49,0xbd6d3cc4,0xbcac3d71,0x3cf13d62,0x3d783c79,0x3d7bbc48,0x3d04bd5c,0xbc95bd75,0xbd67bcdb,0xbd800000,0xbd2c3d3e,0x3bc93d7f,0x3d4e3d18,
0x3c48bd7b,0xbd18bd4e,0xbd7fbbc9,0xbd3e3d2c,0xbcc43d6d,0x3cdb3d67,0x3d753c95,0x3d5cbd04,0x3d0ebd55,0xbc79bd78,0xbd62bcf1,0xbd713cac,0xbd353d35,0x3b493d80,0x3d463d22,0x3d7dbc16,
0x3d35bd35,0x3c16bd7d,0xbcf1bd62,0xbd67bcdb,0xbd7b3c48,0xbd2c3d3e,0xbbc93d7f,0x3d043d5c,0x3d6d3cc4,0x3d78bc79,0x3d22bd46,0x3b49bd80,0xbd0ebd55,0xbd71bcac,0xbd753c95,0xbd183d4e,
0xbd800000,0xbd4e3d18,0xbc953d75,0x3cac3d71,0x3d553d0e,0x3d80bb49,0x3d46bd22,0x3c79bd78,0xbcc4bd6d,0xbd5cbd04,0xbd7f3bc9,0xbd3e3d2c,0xbc483d7b,0x3cdb3d67,0x3d623cf1,0x3d7dbc16,
0x3d553d0e,0x3d7d3c16,0x3d75bc95,0x3d3ebd2c,0xbd353d35,0xbcac3d71,0x3bc93d7f,0x3d043d5c,0xbd7bbc48,0xbd783c79,0xbd463d22,0xbcdb3d67,0x3cc4bd6d,0xbb49bd80,0xbcf1bd62,0xbd4ebd18,
0x3c483d7b,0x3d183d4e,0x3d623cf1,0x3d803b49,0xbd800000,0xbd673cdb,0xbd223d46,0xbc793d78,0xbd0ebd55,0xbd5cbd04,0xbd7fbbc9,0xbd713cac,0x3d6dbcc4,0x3d2cbd3e,0x3c95bd75,0xbc16bd7d,
0xbd6dbcc4,0xbd7dbc16,0xbd7f3bc9,0xbd713cac,0xbd553d0e,0xbd2c3d3e,0xbcf13d62,0xbc793d78,0x3d35bd35,0x3d04bd5c,0x3c95bd75,0x3b49bd80,0xbc48bd7b,0xbcdbbd67,0xbd22bd46,0xbd4ebd18,
0x3cc43d6d,0x3d183d4e,0x3d463d22,0x3d673cdb,0x3d7b3c48,0x3d80bb49,0x3d75bc95,0x3d5cbd04,0xbd800000,0xbd783c79,0xbd623cf1,0xbd3e3d2c,0xbd0e3d55,0xbcac3d71,0xbbc93d7f,0x3c163d7d,
0xbc483d7b,0xbc163d7d,0xbbc93d7f,0xbb493d80,0xbcc43d6d,0xbcac3d71,0xbc953d75,0xbc793d78,0xbd0e3d55,0xbd043d5c,0xbcf13d62,0xbcdb3d67,0xbd353d35,0xbd2c3d3e,0xbd223d46,0xbd183d4e,
0xbd553d0e,0xbd4e3d18,0xbd463d22,0xbd3e3d2c,0xbd6d3cc4,0xbd673cdb,0xbd623cf1,0xbd5c3d04,0xbd7b3c48,0xbd783c79,0xbd753c95,0xbd713cac,0xbd800000,0xbd803b49,0xbd7f3bc9,0xbd7d3c16,
0x3f003f00,0xbf003f00,0x3f003f00,0xbf003f00,0x3f003f00,0xbf003f00,0x3f003f00,0xbf003f00,0x3f003f00,0xbf003f00,0x3f003f00,0xbf003f00,0x3f003f00,0xbf003f00,0x3f003f00,0xbf003f00,
0x3eff3f00,0xbd490000,0x3ea23eb5,0xbec6beb5,0x3ef53efb,0xbe15bdc8,0x3e713e8e,0xbee2bed5,0x3ee23eed,0xbe71be44,0x3e153e44,0xbef5beed,0x3ec63ed5,0xbea2be8e,0x3d493dc8,0xbeffbefb,
0x3efb3f00,0xbdc80000,0xbdc80000,0xbefbbf00,0x3ed53eed,0xbe8ebe44,0xbe8ebe44,0xbed5beed,0x3e8e3eb5,0xbed5beb5,0xbed5beb5,0xbe8ebeb5,0x3dc83e44,0xbefbbeed,0xbefbbeed,0xbdc8be44,
0x3ef53f00,0xbe150000,0xbee2beb5,0xbe71beb5,0x3ea23ed5,0xbec6be8e,0xbeffbefb,0x3d49bdc8,0x3d493e44,0xbeffbeed,0xbec6beed,0x3ea23e44,0xbe71bdc8,0xbee2befb,0xbe15be8e,0x3ef53ed5,
0x3eed3f00,0xbe440000,0xbeedbf00,0x3e440000,0x3e443eb5,0xbeedbeb5,0xbe44beb5,0x3eed3eb5,0xbe440000,0xbeedbf00,0x3e440000,0x3eed3f00,0xbeedbeb5,0xbe44beb5,0x3eed3eb5,0x3e443eb5,
0x3ee23f00,0xbe710000,0xbe15beb5,0x3ef53eb5,0x3d493e8e,0xbeffbed5,0x3ea23dc8,0x3ec63efb,0xbec6be44,0xbea2beed,0x3eff3eed,0xbd493e44,0xbef5befb,0x3e15bdc8,0x3e713ed5,0xbee2be8e,
0x3ed53f00,0xbe8e0000,0x3e8e0000,0x3ed53f00,0xbdc83e44,0xbefbbeed,0x3efb3eed,0xbdc83e44,0xbefbbeb5,0xbdc8beb5,0x3dc83eb5,0xbefbbeb5,0xbe8ebeed,0x3ed53e44,0xbed5be44,0xbe8ebeed,
0x3ec63f00,0xbea20000,0x3eff3eb5,0x3d493eb5,0xbe713dc8,0xbee2befb,0x3e153ed5,0xbef5be8e,0xbef5beed,0x3e15be44,0xbee2be44,0xbe71beed,0x3d49be8e,0x3eff3ed5,0xbea2befb,0x3ec63dc8,
0x3f00,0xbf000000,0x3f00,0xbf000000,0xbf00,0x3f000000,0xbf00,0x3f000000,0x3f00,0xbf000000,0x3f00,0xbf000000,0xbf00,0x3f000000,0xbf00,0x3f000000,
0xbd493f00,0xbeff0000,0xbec63eb5,0xbea2beb5,0x3e15befb,0x3ef53dc8,0x3ee2be8e,0x3e713ed5,0xbe713eed,0xbee2be44,0xbef53e44,0xbe15beed,0x3ea2bed5,0x3ec63e8e,0x3effbdc8,0x3d493efb,
0xbdc83f00,0xbefb0000,0xbefb0000,0x3dc8bf00,0x3e8ebeed,0x3ed53e44,0x3ed53e44,0xbe8e3eed,0xbed53eb5,0xbe8ebeb5,0xbe8ebeb5,0x3ed5beb5,0x3efbbe44,0x3dc83eed,0x3dc83eed,0xbefb3e44,
0xbe153f00,0xbef50000,0xbe71beb5,0x3ee2beb5,0x3ec6bed5,0x3ea23e8e,0xbd493efb,0xbeff3dc8,0xbeff3e44,0xbd49beed,0x3ea2beed,0x3ec63e44,0x3ee23dc8,0xbe713efb,0xbef53e8e,0xbe15bed5,
0xbe443f00,0xbeed0000,0x3e44bf00,0x3eed0000,0x3eedbeb5,0x3e443eb5,0xbeed3eb5,0xbe44beb5,0xbeed0000,0x3e44bf00,0x3eed0000,0xbe443f00,0x3e443eb5,0xbeed3eb5,0xbe44beb5,0x3eedbeb5,
0xbe713f00,0xbee20000,0x3ef5beb5,0x3e153eb5,0x3effbe8e,0x3d493ed5,0xbec6bdc8,0x3ea2befb,0xbea2be44,0x3ec6beed,0xbd493eed,0xbeff3e44,0xbe153efb,0xbef53dc8,0x3ee2bed5,0x3e713e8e,
0xbe8e3f00,0xbed50000,0x3ed50000,0xbe8e3f00,0x3efbbe44,0xbdc83eed,0x3dc8beed,0x3efbbe44,0xbdc8beb5,0x3efbbeb5,0xbefb3eb5,0xbdc8beb5,0xbed53eed,0xbe8ebe44,0x3e8e3e44,0xbed53eed,
0xbea23f00,0xbec60000,0x3d493eb5,0xbeff3eb5,0x3ee2bdc8,0xbe713efb,0x3ef5bed5,0x3e153e8e,0x3e15beed,0x3ef5be44,0xbe71be44,0x3ee2beed,0xbeff3e8e,0x3d49bed5,0xbec63efb,0xbea2bdc8,
0x3eb53f00,0xbeb50000,0x3eb53f00,0xbeb50000,0xbeb50000,0xbeb5bf00,0xbeb50000,0xbeb5bf00,0xbeb5bf00,0x3eb50000,0xbeb5bf00,0x3eb50000,0x3eb50000,0x3eb53f00,0x3eb50000,0x3eb53f00,
0xbeff3f00,0x3d490000,0xbea23eb5,0x3ec6beb5,0xbef53efb,0x3e15bdc8,0xbe713e8e,0x3ee2bed5,0xbee23eed,0x3e71be44,0xbe153e44,0x3ef5beed,0xbec63ed5,0x3ea2be8e,0xbd493dc8,0x3effbefb,
0xbefb3f00,0x3dc80000,0x3dc80000,0x3efbbf00,0xbed53eed,0x3e8ebe44,0x3e8ebe44,0x3ed5beed,0xbe8e3eb5,0x3ed5beb5,0x3ed5beb5,0x3e8ebeb5,0xbdc83e44,0x3efbbeed,0x3efbbeed,0x3dc8be44,
0xbef53f00,0x3e150000,0x3ee2beb5,0x3e71beb5,0xbea23ed5,0x3ec6be8e,0x3effbefb,0xbd49bdc8,0xbd493e44,0x3effbeed,0x3ec6beed,0xbea23e44,0x3e71bdc8,0x3ee2befb,0x3e15be8e,0xbef53ed5,
0xbeed3f00,0x3e440000,0x3eedbf00,0xbe440000,0xbe443eb5,0x3eedbeb5,0x3e44beb5,0xbeed3eb5,0x3e440000,0x3eedbf00,0xbe440000,0xbeed3f00,0x3eedbeb5,0x3e44beb5,0xbeed3eb5,0xbe443eb5,
0xbee23f00,0x3e710000,0x3e15beb5,0xbef53eb5,0xbd493e8e,0x3effbed5,0xbea23dc8,0xbec63efb,0x3ec6be44,0x3ea2beed,0xbeff3eed,0x3d493e44,0x3ef5befb,0xbe15bdc8,0xbe713ed5,0x3ee2be8e,
0xbed53f00,0x3e8e0000,0xbe8e0000,0xbed53f00,0x3dc83e44,0x3efbbeed,0xbefb3eed,0x3dc83e44,0x3efbbeb5,0x3dc8beb5,0xbdc83eb5,0x3efbbeb5,0x3e8ebeed,0xbed53e44,0x3ed5be44,0x3e8ebeed,
0xbec63f00,0x3ea20000,0xbeff3eb5,0xbd493eb5,0x3e713dc8,0x3ee2befb,0xbe153ed5,0x3ef5be8e,0x3ef5beed,0xbe15be44,0x3ee2be44,0x3e71beed,0xbd49be8e,0xbeff3ed5,0x3ea2befb,0xbec63dc8,
0xbeb53f00,0xbeb50000,0xbeb53f00,0xbeb50000,0x3eb50000,0xbeb53f00,0x3eb50000,0xbeb53f00,0x3eb5bf00,0x3eb50000,0x3eb5bf00,0x3eb50000,0xbeb50000,0x3eb5bf00,0xbeb50000,0x3eb5bf00,
0x3d493f00,0x3eff0000,0x3ec63eb5,0x3ea2beb5,0xbe15befb,0xbef53dc8,0xbee2be8e,0xbe713ed5,0x3e713eed,0x3ee2be44,0x3ef53e44,0x3e15beed,0xbea2bed5,0xbec63e8e,0xbeffbdc8,0xbd493efb,
0x3dc83f00,0x3efb0000,0x3efb0000,0xbdc8bf00,0xbe8ebeed,0xbed53e44,0xbed53e44,0x3e8e3eed,0x3ed53eb5,0x3e8ebeb5,0x3e8ebeb5,0xbed5beb5,0xbefbbe44,0xbdc83eed,0xbdc83eed,0x3efb3e44,
0x3e153f00,0x3ef50000,0x3e71beb5,0xbee2beb5,0xbec6bed5,0xbea23e8e,0x3d493efb,0x3eff3dc8,0x3eff3e44,0x3d49beed,0xbea2beed,0xbec63e44,0xbee23dc8,0x3e713efb,0x3ef53e8e,0x3e15bed5,
0x3e443f00,0x3eed0000,0xbe44bf00,0xbeed0000,0xbeedbeb5,0xbe443eb5,0x3eed3eb5,0x3e44beb5,0x3eed0000,0xbe44bf00,0xbeed0000,0x3e443f00,0xbe443eb5,0x3eed3eb5,0x3e44beb5,0xbeedbeb5,
0x3e713f00,0x3ee20000,0xbef5beb5,0xbe153eb5,0xbeffbe8e,0xbd493ed5,0x3ec6bdc8,0xbea2befb,0x3ea2be44,0xbec6beed,0x3d493eed,0x3eff3e44,0x3e153efb,0x3ef53dc8,0xbee2bed5,0xbe713e8e,
0x3e8e3f00,0x3ed50000,0xbed50000,0x3e8e3f00,0xbefbbe44,0x3dc83eed,0xbdc8beed,0xbefbbe44,0x3dc8beb5,0xbefbbeb5,0x3efb3eb5,0x3dc8beb5,0x3ed53eed,0x3e8ebe44,0xbe8e3e44,0x3ed53eed,
0x3ea23f00,0x3ec60000,0xbd493eb5,0x3eff3eb5,0xbee2bdc8,0x3e713efb,0xbef5bed5,0xbe153e8e,0xbe15beed,0xbef5be44,0x3e71be44,0xbee2beed,0x3eff3e8e,0xbd49bed5,0x3ec63efb,0x3ea2bdc8,
0x3f003f00,0xbf003f00,0x3f003f00,0xbf003f00,0x3f003f00,0xbf003f00,0x3f003f00,0xbf003f00,0x3f003f00,0xbf003f00,0x3f003f00,0xbf003f00,0x3f003f00,0xbf003f00,0x3f003f00,0xbf003f00,
0xbd490000,0xbeffbf00,0xbec6beb5,0xbea2beb5,0xbe15bdc8,0xbef5befb,0xbee2bed5,0xbe71be8e,0xbe71be44,0xbee2beed,0xbef5beed,0xbe15be44,0xbea2be8e,0xbec6bed5,0xbeffbefb,0xbd49bdc8,
0xbefbbf00,0x3dc80000,0x3dc80000,0x3efb3f00,0xbed5beed,0x3e8e3e44,0x3e8e3e44,0x3ed53eed,0xbe8ebeb5,0x3ed53eb5,0x3ed53eb5,0x3e8e3eb5,0xbdc8be44,0x3efb3eed,0x3efb3eed,0x3dc83e44,
0x3e150000,0x3ef53f00,0x3e713eb5,0xbee2beb5,0x3ec63e8e,0x3ea23ed5,0xbd493dc8,0xbeffbefb,0x3eff3eed,0x3d493e44,0xbea2be44,0xbec6beed,0x3ee23efb,0xbe71bdc8,0xbef5bed5,0xbe15be8e,
0x3eed3f00,0xbe440000,0xbeedbf00,0x3e440000,0x3e443eb5,0xbeedbeb5,0xbe44beb5,0x3eed3eb5,0xbe440000,0xbeedbf00,0x3e440000,0x3eed3f00,0xbeedbeb5,0xbe44beb5,0x3eed3eb5,0x3e443eb5,
0xbe710000,0xbee2bf00,0x3ef53eb5,0x3e153eb5,0xbeffbed5,0xbd49be8e,0x3ec63efb,0xbea2bdc8,0xbea2beed,0x3ec63e44,0xbd493e44,0xbeffbeed,0x3e15bdc8,0x3ef53efb,0xbee2be8e,0xbe71bed5,
0xbed5bf00,0x3e8e0000,0xbe8e0000,0xbed5bf00,0x3dc8be44,0x3efb3eed,0xbefbbeed,0x3dc8be44,0x3efb3eb5,0x3dc83eb5,0xbdc8beb5,0x3efb3eb5,0x3e8e3eed,0xbed5be44,0x3ed53e44,0x3e8e3eed,
0x3ea20000,0x3ec63f00,0xbd49beb5,0x3eff3eb5,0x3ee23efb,0xbe713dc8,0x3ef53e8e,0x3e153ed5,0xbe153e44,0xbef5beed,0x3e713eed,0xbee2be44,0xbeffbed5,0x3d49be8e,0xbec6bdc8,0xbea2befb,
0x3f00,0xbf000000,0x3f00,0xbf000000,0xbf00,0x3f000000,0xbf00,0x3f000000,0x3f00,0xbf000000,0x3f00,0xbf000000,0xbf00,0x3f000000,0xbf00,0x3f000000,
0xbeff0000,0x3d49bf00,0xbea2beb5,0x3ec6beb5,0x3ef53dc8,0xbe153efb,0x3e713ed5,0xbee23e8e,0xbee2be44,0x3e71beed,0xbe15beed,0x3ef5be44,0x3ec63e8e,0xbea23ed5,0x3d493efb,0xbeff3dc8,
0x3dc8bf00,0x3efb0000,0x3efb0000,0xbdc83f00,0xbe8e3eed,0xbed5be44,0xbed5be44,0x3e8ebeed,0x3ed5beb5,0x3e8e3eb5,0x3e8e3eb5,0xbed53eb5,0xbefb3e44,0xbdc8beed,0xbdc8beed,0x3efbbe44,
0x3ef50000,0xbe153f00,0xbee23eb5,0xbe71beb5,0xbea2be8e,0x3ec6bed5,0x3effbdc8,0xbd493efb,0x3d493eed,0xbeff3e44,0xbec6be44,0x3ea2beed,0x3e71befb,0x3ee23dc8,0x3e153ed5,0xbef53e8e,
0xbe443f00,0xbeed0000,0x3e44bf00,0x3eed0000,0x3eedbeb5,0x3e443eb5,0xbeed3eb5,0xbe44beb5,0xbeed0000,0x3e44bf00,0x3eed0000,0xbe443f00,0x3e443eb5,0xbeed3eb5,0xbe44beb5,0x3eedbeb5,
0xbee20000,0x3e71bf00,0x3e153eb5,0xbef53eb5,0x3d493ed5,0xbeff3e8e,0x3ea2befb,0x3ec63dc8,0x3ec6beed,0x3ea23e44,0xbeff3e44,0x3d49beed,0xbef53dc8,0x3e15befb,0x3e713e8e,0xbee23ed5,
0x3e8ebf00,0x3ed50000,0xbed50000,0x3e8ebf00,0xbefb3e44,0x3dc8beed,0xbdc83eed,0xbefb3e44,0x3dc83eb5,0xbefb3eb5,0x3efbbeb5,0x3dc83eb5,0x3ed5beed,0x3e8e3e44,0xbe8ebe44,0x3ed5beed,
0x3ec60000,0xbea23f00,0x3effbeb5,0x3d493eb5,0x3e71befb,0x3ee2bdc8,0xbe15be8e,0x3ef5bed5,0xbef53e44,0x3e15beed,0xbee23eed,0xbe71be44,0xbd493ed5,0xbeff3e8e,0x3ea23dc8,0xbec63efb,
0x3eb53f00,0xbeb50000,0x3eb53f00,0xbeb50000,0xbeb50000,0xbeb5bf00,0xbeb50000,0xbeb5bf00,0xbeb5bf00,0x3eb50000,0xbeb5bf00,0x3eb50000,0x3eb50000,0x3eb53f00,0x3eb50000,0x3eb53f00,
0x3d490000,0x3effbf00,0x3ec6beb5,0x3ea2beb5,0x3e15bdc8,0x3ef5befb,0x3ee2bed5,0x3e71be8e,0x3e71be44,0x3ee2beed,0x3ef5beed,0x3e15be44,0x3ea2be8e,0x3ec6bed5,0x3effbefb,0x3d49bdc8,
0x3efbbf00,0xbdc80000,0xbdc80000,0xbefb3f00,0x3ed5beed,0xbe8e3e44,0xbe8e3e44,0xbed53eed,0x3e8ebeb5,0xbed53eb5,0xbed53eb5,0xbe8e3eb5,0x3dc8be44,0xbefb3eed,0xbefb3eed,0xbdc83e44,
0xbe150000,0xbef53f00,0xbe713eb5,0x3ee2beb5,0xbec63e8e,0xbea23ed5,0x3d493dc8,0x3effbefb,0xbeff3eed,0xbd493e44,0x3ea2be44,0x3ec6beed,0xbee23efb,0x3e71bdc8,0x3ef5bed5,0x3e15be8e,
0xbeed3f00,0x3e440000,0x3eedbf00,0xbe440000,0xbe443eb5,0x3eedbeb5,0x3e44beb5,0xbeed3eb5,0x3e440000,0x3eedbf00,0xbe440000,0xbeed3f00,0x3eedbeb5,0x3e44beb5,0xbeed3eb5,0xbe443eb5,
0x3e710000,0x3ee2bf00,0xbef53eb5,0xbe153eb5,0x3effbed5,0x3d49be8e,0xbec63efb,0x3ea2bdc8,0x3ea2beed,0xbec63e44,0x3d493e44,0x3effbeed,0xbe15bdc8,0xbef53efb,0x3ee2be8e,0x3e71bed5,
0x3ed5bf00,0xbe8e0000,0x3e8e0000,0x3ed5bf00,0xbdc8be44,0xbefb3eed,0x3efbbeed,0xbdc8be44,0xbefb3eb5,0xbdc83eb5,0x3dc8beb5,0xbefb3eb5,0xbe8e3eed,0x3ed5be44,0xbed53e44,0xbe8e3eed,
0xbea20000,0xbec63f00,0x3d49beb5,0xbeff3eb5,0xbee23efb,0x3e713dc8,0xbef53e8e,0xbe153ed5,0x3e153e44,0x3ef5beed,0xbe713eed,0x3ee2be44,0x3effbed5,0xbd49be8e,0x3ec6bdc8,0x3ea2befb,
0xbeb53f00,0xbeb50000,0xbeb53f00,0xbeb50000,0x3eb50000,0xbeb53f00,0x3eb50000,0xbeb53f00,0x3eb5bf00,0x3eb50000,0x3eb5bf00,0x3eb50000,0xbeb50000,0x3eb5bf00,0xbeb50000,0x3eb5bf00,
0x3eff0000,0xbd49bf00,0x3ea2beb5,0xbec6beb5,0xbef53dc8,0x3e153efb,0xbe713ed5,0x3ee23e8e,0x3ee2be44,0xbe71beed,0x3e15beed,0xbef5be44,0xbec63e8e,0x3ea23ed5,0xbd493efb,0x3eff3dc8,
0xbdc8bf00,0xbefb0000,0xbefb0000,0x3dc83f00,0x3e8e3eed,0x3ed5be44,0x3ed5be44,0xbe8ebeed,0xbed5beb5,0xbe8e3eb5,0xbe8e3eb5,0x3ed53eb5,0x3efb3e44,0x3dc8beed,0x3dc8beed,0xbefbbe44,
0xbef50000,0x3e153f00,0x3ee23eb5,0x3e71beb5,0x3ea2be8e,0xbec6bed5,0xbeffbdc8,0x3d493efb,0xbd493eed,0x3eff3e44,0x3ec6be44,0xbea2beed,0xbe71befb,0xbee23dc8,0xbe153ed5,0x3ef53e8e,
0x3e443f00,0x3eed0000,0xbe44bf00,0xbeed0000,0xbeedbeb5,0xbe443eb5,0x3eed3eb5,0x3e44beb5,0x3eed0000,0xbe44bf00,0xbeed0000,0x3e443f00,0xbe443eb5,0x3eed3eb5,0x3e44beb5,0xbeedbeb5,
0x3ee20000,0xbe71bf00,0xbe153eb5,0x3ef53eb5,0xbd493ed5,0x3eff3e8e,0xbea2befb,0xbec63dc8,0xbec6beed,0xbea23e44,0x3eff3e44,0xbd49beed,0x3ef53dc8,0xbe15befb,0xbe713e8e,0x3ee23ed5,
0xbe8ebf00,0xbed50000,0x3ed50000,0xbe8ebf00,0x3efb3e44,0xbdc8beed,0x3dc83eed,0x3efb3e44,0xbdc83eb5,0x3efb3eb5,0xbefbbeb5,0xbdc83eb5,0xbed5beed,0xbe8e3e44,0x3e8ebe44,0xbed5beed,
0xbec60000,0x3ea23f00,0xbeffbeb5,0xbd493eb5,0xbe71befb,0xbee2bdc8,0x3e15be8e,0xbef5bed5,0x3ef53e44,0xbe15beed,0x3ee23eed,0x3e71be44,0x3d493ed5,0x3eff3e8e,0xbea23dc8,0x3ec63efb,
0x3f003f00,0xbf003f00,0x3f003f00,0xbf003f00,0x3f003f00,0xbf003f00,0x3f003f00,0xbf003f00,0x3f003f00,0xbf003f00,0x3f003f00,0xbf003f00,0x3f003f00,0xbf003f00,0x3f003f00,0xbf003f00,
0xbeffbf00,0x3d490000,0xbea2beb5,0x3ec63eb5,0xbef5befb,0x3e153dc8,0xbe71be8e,0x3ee23ed5,0xbee2beed,0x3e713e44,0xbe15be44,0x3ef53eed,0xbec6bed5,0x3ea23e8e,0xbd49bdc8,0x3eff3efb,
0x3efb3f00,0xbdc80000,0xbdc80000,0xbefbbf00,0x3ed53eed,0xbe8ebe44,0xbe8ebe44,0xbed5beed,0x3e8e3eb5,0xbed5beb5,0xbed5beb5,0xbe8ebeb5,0x3dc83e44,0xbefbbeed,0xbefbbeed,0xbdc8be44,
0xbef5bf00,0x3e150000,0x3ee23eb5,0x3e713eb5,0xbea2bed5,0x3ec63e8e,0x3eff3efb,0xbd493dc8,0xbd49be44,0x3eff3eed,0x3ec63eed,0xbea2be44,0x3e713dc8,0x3ee23efb,0x3e153e8e,0xbef5bed5,
0x3eed3f00,0xbe440000,0xbeedbf00,0x3e440000,0x3e443eb5,0xbeedbeb5,0xbe44beb5,0x3eed3eb5,0xbe440000,0xbeedbf00,0x3e440000,0x3eed3f00,0xbeedbeb5,0xbe44beb5,0x3eed3eb5,0x3e443eb5,
0xbee2bf00,0x3e710000,0x3e153eb5,0xbef5beb5,0xbd49be8e,0x3eff3ed5,0xbea2bdc8,0xbec6befb,0x3ec63e44,0x3ea23eed,0xbeffbeed,0x3d49be44,0x3ef53efb,0xbe153dc8,0xbe71bed5,0x3ee23e8e,
0x3ed53f00,0xbe8e0000,0x3e8e0000,0x3ed53f00,0xbdc83e44,0xbefbbeed,0x3efb3eed,0xbdc83e44,0xbefbbeb5,0xbdc8beb5,0x3dc83eb5,0xbefbbeb5,0xbe8ebeed,0x3ed53e44,0xbed5be44,0xbe8ebeed,
0xbec6bf00,0x3ea20000,0xbeffbeb5,0xbd49beb5,0x3e71bdc8,0x3ee23efb,0xbe15bed5,0x3ef53e8e,0x3ef53eed,0xbe153e44,0x3ee23e44,0x3e713eed,0xbd493e8e,0xbeffbed5,0x3ea23efb,0xbec6bdc8,
0x3f00,0xbf000000,0x3f00,0xbf000000,0xbf00,0x3f000000,0xbf00,0x3f000000,0x3f00,0xbf000000,0x3f00,0xbf000000,0xbf00,0x3f000000,0xbf00,0x3f000000,
0x3d49bf00,0x3eff0000,0x3ec6beb5,0x3ea23eb5,0xbe153efb,0xbef5bdc8,0xbee23e8e,0xbe71bed5,0x3e71beed,0x3ee23e44,0x3ef5be44,0x3e153eed,0xbea23ed5,0xbec6be8e,0xbeff3dc8,0xbd49befb,
0xbdc83f00,0xbefb0000,0xbefb0000,0x3dc8bf00,0x3e8ebeed,0x3ed53e44,0x3ed53e44,0xbe8e3eed,0xbed53eb5,0xbe8ebeb5,0xbe8ebeb5,0x3ed5beb5,0x3efbbe44,0x3dc83eed,0x3dc83eed,0xbefb3e44,
0x3e15bf00,0x3ef50000,0x3e713eb5,0xbee23eb5,0xbec63ed5,0xbea2be8e,0x3d49befb,0x3effbdc8,0x3effbe44,0x3d493eed,0xbea23eed,0xbec6be44,0xbee2bdc8,0x3e71befb,0x3ef5be8e,0x3e153ed5,
0xbe443f00,0xbeed0000,0x3e44bf00,0x3eed0000,0x3eedbeb5,0x3e443eb5,0xbeed3eb5,0xbe44beb5,0xbeed0000,0x3e44bf00,0x3eed0000,0xbe443f00,0x3e443eb5,0xbeed3eb5,0xbe44beb5,0x3eedbeb5,
0x3e71bf00,0x3ee20000,0xbef53eb5,0xbe15beb5,0xbeff3e8e,0xbd49bed5,0x3ec63dc8,0xbea23efb,0x3ea23e44,0xbec63eed,0x3d49beed,0x3effbe44,0x3e15befb,0x3ef5bdc8,0xbee23ed5,0xbe71be8e,
0xbe8e3f00,0xbed50000,0x3ed50000,0xbe8e3f00,0x3efbbe44,0xbdc83eed,0x3dc8beed,0x3efbbe44,0xbdc8beb5,0x3efbbeb5,0xbefb3eb5,0xbdc8beb5,0xbed53eed,0xbe8ebe44,0x3e8e3e44,0xbed53eed,
0x3ea2bf00,0x3ec60000,0xbd49beb5,0x3effbeb5,0xbee23dc8,0x3e71befb,0xbef53ed5,0xbe15be8e,0xbe153eed,0xbef53e44,0x3e713e44,0xbee23eed,0x3effbe8e,0xbd493ed5,0x3ec6befb,0x3ea23dc8,
0x3eb53f00,0xbeb50000,0x3eb53f00,0xbeb50000,0xbeb50000,0xbeb5bf00,0xbeb50000,0xbeb5bf00,0xbeb5bf00,0x3eb50000,0xbeb5bf00,0x3eb50000,0x3eb50000,0x3eb53f00,0x3eb50000,0x3eb53f00,
0x3effbf00,0xbd490000,0x3ea2beb5,0xbec63eb5,0x3ef5befb,0xbe153dc8,0x3e71be8e,0xbee23ed5,0x3ee2beed,0xbe713e44,0x3e15be44,0xbef53eed,0x3ec6bed5,0xbea23e8e,0x3d49bdc8,0xbeff3efb,
0xbefb3f00,0x3dc80000,0x3dc80000,0x3efbbf00,0xbed53eed,0x3e8ebe44,0x3e8ebe44,0x3ed5beed,0xbe8e3eb5,0x3ed5beb5,0x3ed5beb5,0x3e8ebeb5,0xbdc83e44,0x3efbbeed,0x3efbbeed,0x3dc8be44,
0x3ef5bf00,0xbe150000,0xbee23eb5,0xbe713eb5,0x3ea2bed5,0xbec63e8e,0xbeff3efb,0x3d493dc8,0x3d49be44,0xbeff3eed,0xbec63eed,0x3ea2be44,0xbe713dc8,0xbee23efb,0xbe153e8e,0x3ef5bed5,
0xbeed3f00,0x3e440000,0x3eedbf00,0xbe440000,0xbe443eb5,0x3eedbeb5,0x3e44beb5,0xbeed3eb5,0x3e440000,0x3eedbf00,0xbe440000,0xbeed3f00,0x3eedbeb5,0x3e44beb5,0xbeed3eb5,0xbe443eb5,
0x3ee2bf00,0xbe710000,0xbe153eb5,0x3ef5beb5,0x3d49be8e,0xbeff3ed5,0x3ea2bdc8,0x3ec6befb,0xbec63e44,0xbea23eed,0x3effbeed,0xbd49be44,0xbef53efb,0x3e153dc8,0x3e71bed5,0xbee23e8e,
0xbed53f00,0x3e8e0000,0xbe8e0000,0xbed53f00,0x3dc83e44,0x3efbbeed,0xbefb3eed,0x3dc83e44,0x3efbbeb5,0x3dc8beb5,0xbdc83eb5,0x3efbbeb5,0x3e8ebeed,0xbed53e44,0x3ed5be44,0x3e8ebeed,
0x3ec6bf00,0xbea20000,0x3effbeb5,0x3d49beb5,0xbe71bdc8,0xbee23efb,0x3e15bed5,0xbef53e8e,0xbef53eed,0x3e153e44,0xbee23e44,0xbe713eed,0x3d493e8e,0x3effbed5,0xbea23efb,0x3ec6bdc8,
0xbeb53f00,0xbeb50000,0xbeb53f00,0xbeb50000,0x3eb50000,0xbeb53f00,0x3eb50000,0xbeb53f00,0x3eb5bf00,0x3eb50000,0x3eb5bf00,0x3eb50000,0xbeb50000,0x3eb5bf00,0xbeb50000,0x3eb5bf00,
0xbd49bf00,0xbeff0000,0xbec6beb5,0xbea23eb5,0x3e153efb,0x3ef5bdc8,0x3ee23e8e,0x3e71bed5,0xbe71beed,0xbee23e44,0xbef5be44,0xbe153eed,0x3ea23ed5,0x3ec6be8e,0x3eff3dc8,0x3d49befb,
0x3dc83f00,0x3efb0000,0x3efb0000,0xbdc8bf00,0xbe8ebeed,0xbed53e44,0xbed53e44,0x3e8e3eed,0x3ed53eb5,0x3e8ebeb5,0x3e8ebeb5,0xbed5beb5,0xbefbbe44,0xbdc83eed,0xbdc83eed,0x3efb3e44,
0xbe15bf00,0xbef50000,0xbe713eb5,0x3ee23eb5,0x3ec63ed5,0x3ea2be8e,0xbd49befb,0xbeffbdc8,0xbeffbe44,0xbd493eed,0x3ea23eed,0x3ec6be44,0x3ee2bdc8,0xbe71befb,0xbef5be8e,0xbe153ed5,
0x3e443f00,0x3eed0000,0xbe44bf00,0xbeed0000,0xbeedbeb5,0xbe443eb5,0x3eed3eb5,0x3e44beb5,0x3eed0000,0xbe44bf00,0xbeed0000,0x3e443f00,0xbe443eb5,0x3eed3eb5,0x3e44beb5,0xbeedbeb5,
0xbe71bf00,0xbee20000,0x3ef53eb5,0x3e15beb5,0x3eff3e8e,0x3d49bed5,0xbec63dc8,0x3ea23efb,0xbea23e44,0x3ec63eed,0xbd49beed,0xbeffbe44,0xbe15befb,0xbef5bdc8,0x3ee23ed5,0x3e71be8e,
0x3e8e3f00,0x3ed50000,0xbed50000,0x3e8e3f00,0xbefbbe44,0x3dc83eed,0xbdc8beed,0xbefbbe44,0x3dc8beb5,0xbefbbeb5,0x3efb3eb5,0x3dc8beb5,0x3ed53eed,0x3e8ebe44,0xbe8e3e44,0x3ed53eed,
0xbea2bf00,0xbec60000,0x3d49beb5,0xbeffbeb5,0x3ee23dc8,0xbe71befb,0x3ef53ed5,0x3e15be8e,0x3e153eed,0x3ef53e44,0xbe713e44,0x3ee23eed,0xbeffbe8e,0x3d493ed5,0xbec6befb,0xbea23dc8,
0x3f003f00,0xbf003f00,0x3f003f00,0xbf003f00,0x3f003f00,0xbf003f00,0x3f003f00,0xbf003f00,0x3f003f00,0xbf003f00,0x3f003f00,0xbf003f00,0x3f003f00,0xbf003f00,0x3f003f00,0xbf003f00,
0x3d490000,0x3eff3f00,0x3ec63eb5,0x3ea23eb5,0x3e153dc8,0x3ef53efb,0x3ee23ed5,0x3e713e8e,0x3e713e44,0x3ee23eed,0x3ef53eed,0x3e153e44,0x3ea23e8e,0x3ec63ed5,0x3eff3efb,0x3d493dc8,
0xbefbbf00,0x3dc80000,0x3dc80000,0x3efb3f00,0xbed5beed,0x3e8e3e44,0x3e8e3e44,0x3ed53eed,0xbe8ebeb5,0x3ed53eb5,0x3ed53eb5,0x3e8e3eb5,0xbdc8be44,0x3efb3eed,0x3efb3eed,0x3dc83e44,
0xbe150000,0xbef5bf00,0xbe71beb5,0x3ee23eb5,0xbec6be8e,0xbea2bed5,0x3d49bdc8,0x3eff3efb,0xbeffbeed,0xbd49be44,0x3ea23e44,0x3ec63eed,0xbee2befb,0x3e713dc8,0x3ef53ed5,0x3e153e8e,
0x3eed3f00,0xbe440000,0xbeedbf00,0x3e440000,0x3e443eb5,0xbeedbeb5,0xbe44beb5,0x3eed3eb5,0xbe440000,0xbeedbf00,0x3e440000,0x3eed3f00,0xbeedbeb5,0xbe44beb5,0x3eed3eb5,0x3e443eb5,
0x3e710000,0x3ee23f00,0xbef5beb5,0xbe15beb5,0x3eff3ed5,0x3d493e8e,0xbec6befb,0x3ea23dc8,0x3ea23eed,0xbec6be44,0x3d49be44,0x3eff3eed,0xbe153dc8,0xbef5befb,0x3ee23e8e,0x3e713ed5,
0xbed5bf00,0x3e8e0000,0xbe8e0000,0xbed5bf00,0x3dc8be44,0x3efb3eed,0xbefbbeed,0x3dc8be44,0x3efb3eb5,0x3dc83eb5,0xbdc8beb5,0x3efb3eb5,0x3e8e3eed,0xbed5be44,0x3ed53e44,0x3e8e3eed,
0xbea20000,0xbec6bf00,0x3d493eb5,0xbeffbeb5,0xbee2befb,0x3e71bdc8,0xbef5be8e,0xbe15bed5,0x3e15be44,0x3ef53eed,0xbe71beed,0x3ee23e44,0x3eff3ed5,0xbd493e8e,0x3ec63dc8,0x3ea23efb,
0x3f00,0xbf000000,0x3f00,0xbf000000,0xbf00,0x3f000000,0xbf00,0x3f000000,0x3f00,0xbf000000,0x3f00,0xbf000000,0xbf00,0x3f000000,0xbf00,0x3f000000,
0x3eff0000,0xbd493f00,0x3ea23eb5,0xbec63eb5,0xbef5bdc8,0x3e15befb,0xbe71bed5,0x3ee2be8e,0x3ee23e44,0xbe713eed,0x3e153eed,0xbef53e44,0xbec6be8e,0x3ea2bed5,0xbd49befb,0x3effbdc8,
0x3dc8bf00,0x3efb0000,0x3efb0000,0xbdc83f00,0xbe8e3eed,0xbed5be44,0xbed5be44,0x3e8ebeed,0x3ed5beb5,0x3e8e3eb5,0x3e8e3eb5,0xbed53eb5,0xbefb3e44,0xbdc8beed,0xbdc8beed,0x3efbbe44,
0xbef50000,0x3e15bf00,0x3ee2beb5,0x3e713eb5,0x3ea23e8e,0xbec63ed5,0xbeff3dc8,0x3d49befb,0xbd49beed,0x3effbe44,0x3ec63e44,0xbea23eed,0xbe713efb,0xbee2bdc8,0xbe15bed5,0x3ef5be8e,
0xbe443f00,0xbeed0000,0x3e44bf00,0x3eed0000,0x3eedbeb5,0x3e443eb5,0xbeed3eb5,0xbe44beb5,0xbeed0000,0x3e44bf00,0x3eed0000,0xbe443f00,0x3e443eb5,0xbeed3eb5,0xbe44beb5,0x3eedbeb5,
0x3ee20000,0xbe713f00,0xbe15beb5,0x3ef5beb5,0xbd49bed5,0x3effbe8e,0xbea23efb,0xbec6bdc8,0xbec63eed,0xbea2be44,0x3effbe44,0xbd493eed,0x3ef5bdc8,0xbe153efb,0xbe71be8e,0x3ee2bed5,
0x3e8ebf00,0x3ed50000,0xbed50000,0x3e8ebf00,0xbefb3e44,0x3dc8beed,0xbdc83eed,0xbefb3e44,0x3dc83eb5,0xbefb3eb5,0x3efbbeb5,0x3dc83eb5,0x3ed5beed,0x3e8e3e44,0xbe8ebe44,0x3ed5beed,
0xbec60000,0x3ea2bf00,0xbeff3eb5,0xbd49beb5,0xbe713efb,0xbee23dc8,0x3e153e8e,0xbef53ed5,0x3ef5be44,0xbe153eed,0x3ee2beed,0x3e713e44,0x3d49bed5,0x3effbe8e,0xbea2bdc8,0x3ec6befb,
0x3eb53f00,0xbeb50000,0x3eb53f00,0xbeb50000,0xbeb50000,0xbeb5bf00,0xbeb50000,0xbeb5bf00,0xbeb5bf00,0x3eb50000,0xbeb5bf00,0x3eb50000,0x3eb50000,0x3eb53f00,0x3eb50000,0x3eb53f00,
0xbd490000,0xbeff3f00,0xbec63eb5,0xbea23eb5,0xbe153dc8,0xbef53efb,0xbee23ed5,0xbe713e8e,0xbe713e44,0xbee23eed,0xbef53eed,0xbe153e44,0xbea23e8e,0xbec63ed5,0xbeff3efb,0xbd493dc8,
0x3efbbf00,0xbdc80000,0xbdc80000,0xbefb3f00,0x3ed5beed,0xbe8e3e44,0xbe8e3e44,0xbed53eed,0x3e8ebeb5,0xbed53eb5,0xbed53eb5,0xbe8e3eb5,0x3dc8be44,0xbefb3eed,0xbefb3eed,0xbdc83e44,
0x3e150000,0x3ef5bf00,0x3e71beb5,0xbee23eb5,0x3ec6be8e,0x3ea2bed5,0xbd49bdc8,0xbeff3efb,0x3effbeed,0x3d49be44,0xbea23e44,0xbec63eed,0x3ee2befb,0xbe713dc8,0xbef53ed5,0xbe153e8e,
0xbeed3f00,0x3e440000,0x3eedbf00,0xbe440000,0xbe443eb5,0x3eedbeb5,0x3e44beb5,0xbeed3eb5,0x3e440000,0x3eedbf00,0xbe440000,0xbeed3f00,0x3eedbeb5,0x3e44beb5,0xbeed3eb5,0xbe443eb5,
0xbe710000,0xbee23f00,0x3ef5beb5,0x3e15beb5,0xbeff3ed5,0xbd493e8e,0x3ec6befb,0xbea23dc8,0xbea23eed,0x3ec6be44,0xbd49be44,0xbeff3eed,0x3e153dc8,0x3ef5befb,0xbee23e8e,0xbe713ed5,
0x3ed5bf00,0xbe8e0000,0x3e8e0000,0x3ed5bf00,0xbdc8be44,0xbefb3eed,0x3efbbeed,0xbdc8be44,0xbefb3eb5,0xbdc83eb5,0x3dc8beb5,0xbefb3eb5,0xbe8e3eed,0x3ed5be44,0xbed53e44,0xbe8e3eed,
0x3ea20000,0x3ec6bf00,0xbd493eb5,0x3effbeb5,0x3ee2befb,0xbe71bdc8,0x3ef5be8e,0x3e15bed5,0xbe15be44,0xbef53eed,0x3e71beed,0xbee23e44,0xbeff3ed5,0x3d493e8e,0xbec63dc8,0xbea23efb,
0xbeb53f00,0xbeb50000,0xbeb53f00,0xbeb50000,0x3eb50000,0xbeb53f00,0x3eb50000,0xbeb53f00,0x3eb5bf00,0x3eb50000,0x3eb5bf00,0x3eb50000,0xbeb50000,0x3eb5bf00,0xbeb50000,0x3eb5bf00,
0xbeff0000,0x3d493f00,0xbea23eb5,0x3ec63eb5,0x3ef5bdc8,0xbe15befb,0x3e71bed5,0xbee2be8e,0xbee23e44,0x3e713eed,0xbe153eed,0x3ef53e44,0x3ec6be8e,0xbea2bed5,0x3d49befb,0xbeffbdc8,
0xbdc8bf00,0xbefb0000,0xbefb0000,0x3dc83f00,0x3e8e3eed,0x3ed5be44,0x3ed5be44,0xbe8ebeed,0xbed5beb5,0xbe8e3eb5,0xbe8e3eb5,0x3ed53eb5,0x3efb3e44,0x3dc8beed,0x3dc8beed,0xbefbbe44,
0x3ef50000,0xbe15bf00,0xbee2beb5,0xbe713eb5,0xbea23e8e,0x3ec63ed5,0x3eff3dc8,0xbd49befb,0x3d49beed,0xbeffbe44,0xbec63e44,0x3ea23eed,0x3e713efb,0x3ee2bdc8,0x3e15bed5,0xbef5be8e,
0x3e443f00,0x3eed0000,0xbe44bf00,0xbeed0000,0xbeedbeb5,0xbe443eb5,0x3eed3eb5,0x3e44beb5,0x3eed0000,0xbe44bf00,0xbeed0000,0x3e443f00,0xbe443eb5,0x3eed3eb5,0x3e44beb5,0xbeedbeb5,
0xbee20000,0x3e713f00,0x3e15beb5,0xbef5beb5,0x3d49bed5,0xbeffbe8e,0x3ea23efb,0x3ec6bdc8,0x3ec63eed,0x3ea2be44,0xbeffbe44,0x3d493eed,0xbef5bdc8,0x3e153efb,0x3e71be8e,0xbee2bed5,
0xbe8ebf00,0xbed50000,0x3ed50000,0xbe8ebf00,0x3efb3e44,0xbdc8beed,0x3dc83eed,0x3efb3e44,0xbdc83eb5,0x3efb3eb5,0xbefbbeb5,0xbdc83eb5,0xbed5beed,0xbe8e3e44,0x3e8ebe44,0xbed5beed,
0x3ec60000,0xbea2bf00,0x3eff3eb5,0x3d49beb5,0x3e713efb,0x3ee23dc8,0xbe153e8e,0x3ef53ed5,0xbef5be44,0x3e153eed,0xbee2beed,0xbe713e44,0xbd49bed5,0xbeffbe8e,0x3ea2bdc8,0xbec6befb,
0x3f800000,0x0,0x3f800000,0x0,0x3f800000,0x0,0x3f800000,0x0,0x3f800000,0x0,0x3f800000,0x0,0x3f800000,0x0,0x3f800000,0x0,
0x3f800000,0x0,0x3f7fec43,0xbcc90ab0,0x3f7fb10f,0xbd48fb30,0x3f7f4e6d,0xbd96a905,0x3f7ec46d,0xbdc8bd36,0x3f7e1324,0xbdfab273,0x3f7d3aac,0xbe164083,0x3f7c3b28,0xbe2f10a2,
0x3f800000,0x0,0x3f7ffec4,0xbbc90f88,0x3f7ffb11,0xbc490e90,0x3f7ff4e6,0xbc96c9b6,0x3f7fec43,0xbcc90ab0,0x3f7fe129,0xbcfb49ba,0x3f7fd397,0xbd16c32c,0x3f7fc38f,0xbd2fe007,
0x3f800000,0x0,0x3f7fe129,0xbcfb49ba,0x3f7f84ab,0xbd7b2b74,0x3f7eea9d,0xbdbc3ac3,0x3f7e1324,0xbdfab273,0x3f7cfe73,0xbe1c76de,0x3f7baccd,0xbe3b6ecf,0x3f7a1e84,0xbe5a3997,
0x3f800000,0x0,0x3f7ffb11,0xbc490e90,0x3f7fec43,0xbcc90ab0,0x3f7fd397,0xbd16c32c,0x3f7fb10f,0xbd48fb30,0x3f7f84ab,0xbd7b2b74,0x3f7f4e6d,0xbd96a905,0x3f7f0e58,0xbdafb680,
0x3f800000,0x0,0x3f7fd397,0xbd16c32c,0x3f7f4e6d,0xbd96a905,0x3f7e70b0,0xbde1bc2e,0x3f7d3aac,0xbe164083,0x3f7baccd,0xbe3b6ecf,0x3f79c79d,0xbe605c13,0x3f778bc5,0xbe827dc0,
0x3f800000,0x0,0x3f7ff4e6,0xbc96c9b6,0x3f7fd397,0xbd16c32c,0x3f7f9c18,0xbd621469,0x3f7f4e6d,0xbd96a905,0x3f7eea9d,0xbdbc3ac3,0x3f7e70b0,0xbde1bc2e,0x3f7de0b1,0xbe039502,
0x3f800000,0x0,0x3f7fc38f,0xbd2fe007,0x3f7f0e58,0xbdafb680,0x3f7de0b1,0xbe039502,0x3f7c3b28,0xbe2f10a2,0x3f7a1e84,0xbe5a3997,0x3f778bc5,0xbe827dc0,0x3f748422,0xbe97a117,
0x3f800000,0x0,0x3f7fb10f,0xbd48fb30,0x3f7ec46d,0xbdc8bd36,0x3f7d3aac,0xbe164083,0x3f7b14be,0xbe47c5c2,0x3f7853f8,0xbe78cfcc,0x3f74fa0b,0xbe94a031,0x3f710908,0xbeac7cd4,
0x3f800000,0x0,0x3f7f4e6d,0xbd96a905,0x3f7d3aac,0xbe164083,0x3f79c79d,0xbe605c13,0x3f74fa0b,0xbe94a031,0x3f6ed89e,0xbeb8442a,0x3f676bd8,0xbedae880,0x3f5ebe05,0xbefc5d27,
0x3f800000,0x0,0x3f7f9c18,0xbd621469,0x3f7e70b0,0xbde1bc2e,0x3f7c7eb0,0xbe28defc,0x3f79c79d,0xbe605c13,0x3f764d97,0xbe8b9507,0x3f721352,0xbea68f12,0x3f6d1c1d,0xbec1071e,
0x3f800000,0x0,0x3f7f2f9d,0xbda3308c,0x3f7cbfc9,0xbe22abb6,0x3f78b47b,0xbe72b651,0x3f731447,0xbea09ae5,0x3f6be858,0xbec6d529,0x3f633c5a,0xbeebcbbb,0x3f591e6a,0xbf07a136,
0x3f800000,0x0,0x3f7f84ab,0xbd7b2b74,0x3f7e1324,0xbdfab273,0x3f7baccd,0xbe3b6ecf,0x3f7853f8,0xbe78cfcc,0x3f740bdd,0xbe9aa086,0x3f6ed89e,0xbeb8442a,0x3f68bf3c,0xbed53641,
0x3f800000,0x0,0x3f7f0e58,0xbdafb680,0x3f7c3b28,0xbe2f10a2,0x3f778bc5,0xbe827dc0,0x3f710908,0xbeac7cd4,0x3f68bf3c,0xbed53641,0x3f5ebe05,0xbefc5d27,0x3f531849,0xbf10d3cd,
0x3f800000,0x0,0x3f7f6ac7,0xbd8a200a,0x3f7dabcc,0xbe09cf86,0x3f7ac516,0xbe4dee60,0x3f76ba07,0xbe888e93,0x3f718f57,0xbea986c4,0x3f6b4b0c,0xbec9b953,0x3f63f473,0xbee900b7,
0x3f800000,0x0,0x3f7eea9d,0xbdbc3ac3,0x3f7baccd,0xbe3b6ecf,0x3f764d97,0xbe8b9507,0x3f6ed89e,0xbeb8442a,0x3f655e0b,0xbee363fa,0x3f59f26a,0xbf064b82,0x3f4cae79,0xbf19c200,
0x3f800000,0x0,0x3f7ec46d,0xbdc8bd36,0x3f7b14be,0xbe47c5c2,0x3f74fa0b,0xbe94a031,0x3f6c835e,0xbec3ef15,0x3f61c598,0xbef15aea,0x3f54db31,0xbf0e39da,0x3f45e403,0xbf226799,
0x3f800000,0x0,0x3f7e1324,0xbdfab273,0x3f7853f8,0xbe78cfcc,0x3f6ed89e,0xbeb8442a,0x3f61c598,0xbef15aea,0x3f514d3d,0xbf13682a,0x3f3daef9,0xbf2beb4a,0x3f273656,0xbf41d870,
0x3f800000,0x0,0x3f7e9bc9,0xbdd53db9,0x3f7a7302,0xbe541501,0x3f73913f,0xbe9d9e78,0x3f6a09a7,0xbecf7bca,0x3f5df6be,0xbeff17b2,0x3f4f7a1f,0xbf15f6d9,0x3f3ebc1b,0xbf2ac082,
0x3f800000,0x0,0x3f7de0b1,0xbe039502,0x3f778bc5,0xbe827dc0,0x3f6d1c1d,0xbec1071e,0x3f5ebe05,0xbefc5d27,0x3f4cae79,0xbf19c200,0x3f373a23,0xbf32c8c9,0x3f1ebc12,0xbf48d8b3,
0x3f800000,0x0,0x3f7e70b0,0xbde1bc2e,0x3f79c79d,0xbe605c13,0x3f721352,0xbea68f12,0x3f676bd8,0xbedae880,0x3f59f26a,0xbf064b82,0x3f49d112,0xbf1d7fd1,0x3f373a23,0xbf32c8c9,
0x3f800000,0x0,0x3f7dabcc,0xbe09cf86,0x3f76ba07,0xbe888e93,0x3f6b4b0c,0xbec9b953,0x3f5b941a,0xbf039c3d,0x3f47de65,0xbf1ff6cb,0x3f3085bb,0xbf396842,0x3f15f6d9,0xbf4f7a1f,
0x3f800000,0x0,0x3f7e4323,0xbdee3876,0x3f791298,0xbe6c9a7f,0x3f708066,0xbeaf713a,0x3f64aa59,0xbee63375,0x3f55b993,0xbf0cead0,0x3f43e200,0xbf24d225,0x3f2f61a5,0xbf3a7ca4,
0x3f800000,0x0,0x3f7d7474,0xbe1008b7,0x3f75dec6,0xbe8e9a22,0x3f696591,0xbed25a09,0x3f584853,0xbf08f59b,0x3f42de29,0xbf26050a,0x3f299415,0xbf3fc767,0x3f0cead0,0xbf55b993,
0x3f800000,0x0,0x3f7d3aac,0xbe164083,0x3f74fa0b,0xbe94a031,0x3f676bd8,0xbedae880,0x3f54db31,0xbf0e39da,0x3f3daef9,0xbf2beb4a,0x3f226799,0xbf45e403,0x3f039c3d,0xbf5b941a,
0x3f800000,0x0,0x3f7c3b28,0xbe2f10a2,0x3f710908,0xbeac7cd4,0x3f5ebe05,0xbefc5d27,0x3f45e403,0xbf226799,0x3f273656,0xbf41d870,0x3f039c3d,0xbf5b941a,0x3eb8442a,0xbf6ed89e,
0x3f800000,0x0,0x3f7cfe73,0xbe1c76de,0x3f740bdd,0xbe9aa086,0x3f655e0b,0xbee363fa,0x3f514d3d,0xbf13682a,0x3f385216,0xbf31a81d,0x3f1b02c6,0xbf4bbbf8,0x3ef41f07,0xbf6106f2,
0x3f800000,0x0,0x3f7bf531,0xbe354098,0x3f6ff573,0xbeb263ef,0x3f5c61c7,0xbf0242b1,0x3f41d870,0xbf273656,0x3f212ff9,0xbf46e22a,0x3ef6e0cb,0xbf604621,0x3ea395c5,0xbf7294f8,
0x3f800000,0x0,0x3f7cbfc9,0xbe22abb6,0x3f731447,0xbea09ae5,0x3f633c5a,0xbeebcbbb,0x3f4d9f02,0xbf187fc0,0x3f32c8c9,0xbf373a23,0x3f13682a,0xbf514d3d,0x3ee0924f,0xbf660f88,
0x3f800000,0x0,0x3f7baccd,0xbe3b6ecf,0x3f6ed89e,0xbeb8442a,0x3f59f26a,0xbf064b82,0x3f3daef9,0xbf2beb4a,0x3f1b02c6,0xbf4bbbf8,0x3ee63375,0xbf64aa59,0x3e8e9a22,0xbf75dec6,
0x3f800000,0x0,0x3f7c7eb0,0xbe28defc,0x3f721352,0xbea68f12,0x3f6106f2,0xbef41f07,0x3f49d112,0xbf1d7fd1,0x3f2d1469,0xbf3ca003,0x3f0b9a6b,0xbf5695e5,0x3ecc9b8b,0xbf6aab7b,
0x3f800000,0x0,0x3f7b61fc,0xbe419b37,0x3f6db293,0xbebe1d4a,0x3f577026,0xbf0a48ad,0x3f396842,0xbf3085bb,0x3f14b039,0xbf5064af,0x3ed53641,0xbf68bf3c,0x3e72b651,0xbf78b47b,
0x3f800000,0x0,0x3f800000,0x0,0x3f800000,0x0,0x3f800000,0x0,0x3f800000,0x0,0x3f800000,0x0,0x3f800000,0x0,0x3f800000,0x0,
0x3f7b14be,0xbe47c5c2,0x3f79c79d,0xbe605c13,0x3f7853f8,0xbe78cfcc,0x3f76ba07,0xbe888e93,0x3f74fa0b,0xbe94a031,0x3f731447,0xbea09ae5,0x3f710908,0xbeac7cd4,0x3f6ed89e,0xbeb8442a,
0x3f7fb10f,0xbd48fb30,0x3f7f9c18,0xbd621469,0x3f7f84ab,0xbd7b2b74,0x3f7f6ac7,0xbd8a200a,0x3f7f4e6d,0xbd96a905,0x3f7f2f9d,0xbda3308c,0x3f7f0e58,0xbdafb680,0x3f7eea9d,0xbdbc3ac3,
0x3f7853f8,0xbe78cfcc,0x3f764d97,0xbe8b9507,0x3f740bdd,0xbe9aa086,0x3f718f57,0xbea986c4,0x3f6ed89e,0xbeb8442a,0x3f6be858,0xbec6d529,0x3f68bf3c,0xbed53641,0x3f655e0b,0xbee363fa,
0x3f7ec46d,0xbdc8bd36,0x3f7e70b0,0xbde1bc2e,0x3f7e1324,0xbdfab273,0x3f7dabcc,0xbe09cf86,0x3f7d3aac,0xbe164083,0x3f7cbfc9,0xbe22abb6,0x3f7c3b28,0xbe2f10a2,0x3f7baccd,0xbe3b6ecf,
0x3f74fa0b,0xbe94a031,0x3f721352,0xbea68f12,0x3f6ed89e,0xbeb8442a,0x3f6b4b0c,0xbec9b953,0x3f676bd8,0xbedae880,0x3f633c5a,0xbeebcbbb,0x3f5ebe05,0xbefc5d27,0x3f59f26a,0xbf064b82,
0x3f7d3aac,0xbe164083,0x3f7c7eb0,0xbe28defc,0x3f7baccd,0xbe3b6ecf,0x3f7ac516,0xbe4dee60,0x3f79c79d,0xbe605c13,0x3f78b47b,0xbe72b651,0x3f778bc5,0xbe827dc0,0x3f764d97,0xbe8b9507,
0x3f710908,0xbeac7cd4,0x3f6d1c1d,0xbec1071e,0x3f68bf3c,0xbed53641,0x3f63f473,0xbee900b7,0x3f5ebe05,0xbefc5d27,0x3f591e6a,0xbf07a136,0x3f531849,0xbf10d3cd,0x3f4cae79,0xbf19c200,
0x3f6c835e,0xbec3ef15,0x3f676bd8,0xbedae880,0x3f61c598,0xbef15aea,0x3f5b941a,0xbf039c3d,0x3f54db31,0xbf0e39da,0x3f4d9f02,0xbf187fc0,0x3f45e403,0xbf226799,0x3f3daef9,0xbf2beb4a,
0x3f54db31,0xbf0e39da,0x3f49d112,0xbf1d7fd1,0x3f3daef9,0xbf2beb4a,0x3f3085bb,0xbf396842,0x3f226799,0xbf45e403,0x3f13682a,0xbf514d3d,0x3f039c3d,0xbf5b941a,0x3ee63375,0xbf64aa59,
0x3f676bd8,0xbedae880,0x3f6106f2,0xbef41f07,0x3f59f26a,0xbf064b82,0x3f5233c6,0xbf121eb0,0x3f49d112,0xbf1d7fd1,0x3f40d0da,0xbf286605,0x3f373a23,0xbf32c8c9,0x3f2d1469,0xbf3ca003,
0x3f4d9f02,0xbf187fc0,0x3f40d0da,0xbf286605,0x3f32c8c9,0xbf373a23,0x3f239da9,0xbf44e3f5,0x3f13682a,0xbf514d3d,0x3f0242b1,0xbf5c61c7,0x3ee0924f,0xbf660f88,0x3ebb31a0,0xbf6e46be,
0x3f61c598,0xbef15aea,0x3f59f26a,0xbf064b82,0x3f514d3d,0xbf13682a,0x3f47de65,0xbf1ff6cb,0x3f3daef9,0xbf2beb4a,0x3f32c8c9,0xbf373a23,0x3f273656,0xbf41d870,0x3f1b02c6,0xbf4bbbf8,
0x3f45e403,0xbf226799,0x3f373a23,0xbf32c8c9,0x3f273656,0xbf41d870,0x3f15f6d9,0xbf4f7a1f,0x3f039c3d,0xbf5b941a,0x3ee0924f,0xbf660f88,0x3eb8442a,0xbf6ed89e,0x3e8e9a22,0xbf75dec6,
0x3f5b941a,0xbf039c3d,0x3f5233c6,0xbf121eb0,0x3f47de65,0xbf1ff6cb,0x3f3ca003,0xbf2d1469,0x3f3085bb,0xbf396842,0x3f239da9,0xbf44e3f5,0x3f15f6d9,0xbf4f7a1f,0x3f07a136,0xbf591e6a,
0x3f3daef9,0xbf2beb4a,0x3f2d1469,0xbf3ca003,0x3f1b02c6,0xbf4bbbf8,0x3f07a136,0xbf591e6a,0x3ee63375,0xbf64aa59,0x3ebb31a0,0xbf6e46be,0x3e8e9a22,0xbf75dec6,0x3e419b37,0xbf7b61fc,
0x3f3504f3,0xbf3504f3,0x3f226799,0xbf45e403,0x3f0e39da,0xbf54db31,0x3ef15aea,0xbf61c598,0x3ec3ef15,0xbf6c835e,0x3e94a031,0xbf74fa0b,0x3e47c5c2,0xbf7b14be,0x3dc8bd36,0xbf7ec46d,
0x3f0e39da,0xbf54db31,0x3ee63375,0xbf64aa59,0x3eac7cd4,0xbf710908,0x3e605c13,0xbf79c79d,0x3dc8bd36,0xbf7ec46d,0xbcc90ab0,0xbf7fec43,0xbe164083,0xbf7d3aac,0xbe888e93,0xbf76ba07,
0x3f2beb4a,0xbf3daef9,0x3f173c07,0xbf4e8d90,0x3f00e7e4,0xbf5d2d53,0x3ed25a09,0xbf696591,0x3ea09ae5,0xbf731447,0x3e5a3997,0xbf7a1e84,0x3de1bc2e,0xbf7e70b0,0x3bc90f88,0xbf7ffec4,
0x3f039c3d,0xbf5b941a,0x3ecc9b8b,0xbf6aab7b,0x3e8e9a22,0xbf75dec6,0x3e1c76de,0xbf7cfe73,0x3cc90ab0,0xbf7fec43,0xbdd53db9,0xbf7e9bc9,0xbe6c9a7f,0xbf791298,0xbeb554ec,0xbf6f6830,
0x3f226799,0xbf45e403,0x3f0b9a6b,0xbf5695e5,0x3ee63375,0xbf64aa59,0x3eb263ef,0xbf6ff573,0x3e78cfcc,0xbf7853f8,0x3e09cf86,0xbf7dabcc,0x3cc90ab0,0xbf7fec43,0xbdafb680,0xbf7f0e58,
0x3ef15aea,0xbf61c598,0x3eb263ef,0xbf6ff573,0x3e605c13,0xbf79c79d,0x3dafb680,0xbf7f0e58,0xbd48fb30,0xbf7fb10f,0xbe3b6ecf,0xbf7baccd,0xbea09ae5,0xbf731447,0xbee0924f,0xbf660f88,
0x3f187fc0,0xbf4d9f02,0x3eff17b2,0xbf5df6be,0x3ec9b953,0xbf6b4b0c,0x3e919ddd,0xbf756d97,0x3e2f10a2,0xbf7c3b28,0x3d621469,0xbf7f9c18,0xbd7b2b74,0xbf7f84ab,0xbe354098,0xbf7bf531,
0x3edae880,0xbf676bd8,0x3e97a117,0xbf748422,0x3e22abb6,0xbf7cbfc9,0x3c96c9b6,0xbf7ff4e6,0xbdfab273,0xbf7e1324,0xbe8586ce,0xbf772417,0xbec9b953,0xbf6b4b0c,0xbf04f484,0xbf5ac450,
0x3ec3ef15,0xbf6c835e,0x3e78cfcc,0xbf7853f8,0x3dc8bd36,0xbf7ec46d,0xbd48fb30,0xbf7fb10f,0xbe47c5c2,0xbf7b14be,0xbeac7cd4,0xbf710908,0xbef15aea,0xbf61c598,0xbf187fc0,0xbf4d9f02,
0x3e47c5c2,0xbf7b14be,0x3cc90ab0,0xbf7fec43,0xbe164083,0xbf7d3aac,0xbea09ae5,0xbf731447,0xbef15aea,0xbf61c598,0xbf1d7fd1,0xbf49d112,0xbf3daef9,0xbf2beb4a,0xbf584853,0xbf08f59b,
0x3eac7cd4,0xbf710908,0x3e419b37,0xbf7b61fc,0x3d16c32c,0xbf7fd397,0xbdee3876,0xbf7e4323,0xbe888e93,0xbf76ba07,0xbed25a09,0xbf696591,0xbf0b9a6b,0xbf5695e5,0xbf2ac082,0xbf3ebc1b,
0x3e164083,0xbf7d3aac,0xbcfb49ba,0xbf7fe129,0xbe541501,0xbf7a7302,0xbec1071e,0xbf6d1c1d,0xbf08f59b,0xbf584853,0xbf2d1469,0xbf3ca003,0xbf4bbbf8,0xbf1b02c6,0xbf63f473,0xbee900b7,
0x3e94a031,0xbf74fa0b,0x3e09cf86,0xbf7dabcc,0xbcc90ab0,0xbf7fec43,0xbe3b6ecf,0xbf7baccd,0xbeac7cd4,0xbf710908,0xbef6e0cb,0xbf604621,0xbf1d7fd1,0xbf49d112,0xbf3b8f3b,0xbf2e3bde,
0x3dc8bd36,0xbf7ec46d,0xbdafb680,0xbf7f0e58,0xbe888e93,0xbf76ba07,0xbee0924f,0xbf660f88,0xbf187fc0,0xbf4d9f02,0xbf3b8f3b,0xbf2e3bde,0xbf584853,0xbf08f59b,0xbf6db293,0xbebe1d4a,
0x3e78cfcc,0xbf7853f8,0x3da3308c,0xbf7f2f9d,0xbdafb680,0xbf7f0e58,0xbe7ee6e1,0xbf77f110,0xbecf7bca,0xbf6a09a7,0xbf0cead0,0xbf55b993,0xbf2e3bde,0xbf3b8f3b,0xbf4ac77f,0xbf1c420c,
0x3d48fb30,0xbf7fb10f,0xbe1008b7,0xbf7d7474,0xbea68f12,0xbf721352,0xbeff17b2,0xbf5df6be,0xbf273656,0xbf41d870,0xbf48d8b3,0xbf1ebc12,0xbf633c5a,0xbeebcbbb,0xbf756d97,0xbe919ddd,
0x3f800000,0x0,0x3f800000,0x0,0x3f800000,0x0,0x3f800000,0x0,0x3f800000,0x0,0x3f800000,0x0,0x3f800000,0x0,0x3f800000,0x0,
0x3f6c835e,0xbec3ef15,0x3f6a09a7,0xbecf7bca,0x3f676bd8,0xbedae880,0x3f64aa59,0xbee63375,0x3f61c598,0xbef15aea,0x3f5ebe05,0xbefc5d27,0x3f5b941a,0xbf039c3d,0x3f584853,0xbf08f59b,
0x3f7ec46d,0xbdc8bd36,0x3f7e9bc9,0xbdd53db9,0x3f7e70b0,0xbde1bc2e,0x3f7e4323,0xbdee3876,0x3f7e1324,0xbdfab273,0x3f7de0b1,0xbe039502,0x3f7dabcc,0xbe09cf86,0x3f7d7474,0xbe1008b7,
0x3f61c598,0xbef15aea,0x3f5df6be,0xbeff17b2,0x3f59f26a,0xbf064b82,0x3f55b993,0xbf0cead0,0x3f514d3d,0xbf13682a,0x3f4cae79,0xbf19c200,0x3f47de65,0xbf1ff6cb,0x3f42de29,0xbf26050a,
0x3f7b14be,0xbe47c5c2,0x3f7a7302,0xbe541501,0x3f79c79d,0xbe605c13,0x3f791298,0xbe6c9a7f,0x3f7853f8,0xbe78cfcc,0x3f778bc5,0xbe827dc0,0x3f76ba07,0xbe888e93,0x3f75dec6,0xbe8e9a22,
0x3f54db31,0xbf0e39da,0x3f4f7a1f,0xbf15f6d9,0x3f49d112,0xbf1d7fd1,0x3f43e200,0xbf24d225,0x3f3daef9,0xbf2beb4a,0x3f373a23,0xbf32c8c9,0x3f3085bb,0xbf396842,0x3f299415,0xbf3fc767,
0x3f74fa0b,0xbe94a031,0x3f73913f,0xbe9d9e78,0x3f721352,0xbea68f12,0x3f708066,0xbeaf713a,0x3f6ed89e,0xbeb8442a,0x3f6d1c1d,0xbec1071e,0x3f6b4b0c,0xbec9b953,0x3f696591,0xbed25a09,
0x3f45e403,0xbf226799,0x3f3ebc1b,0xbf2ac082,0x3f373a23,0xbf32c8c9,0x3f2f61a5,0xbf3a7ca4,0x3f273656,0xbf41d870,0x3f1ebc12,0xbf48d8b3,0x3f15f6d9,0xbf4f7a1f,0x3f0cead0,0xbf55b993,
0x3f3504f3,0xbf3504f3,0x3f2beb4a,0xbf3daef9,0x3f226799,0xbf45e403,0x3f187fc0,0xbf4d9f02,0x3f0e39da,0xbf54db31,0x3f039c3d,0xbf5b941a,0x3ef15aea,0xbf61c598,0x3edae880,0xbf676bd8,
0x3ec3ef15,0xbf6c835e,0x3ea09ae5,0xbf731447,0x3e78cfcc,0xbf7853f8,0x3e2f10a2,0xbf7c3b28,0x3dc8bd36,0xbf7ec46d,0x3cc90ab0,0xbf7fec43,0xbd48fb30,0xbf7fb10f,0xbdfab273,0xbf7e1324,
0x3f226799,0xbf45e403,0x3f173c07,0xbf4e8d90,0x3f0b9a6b,0xbf5695e5,0x3eff17b2,0xbf5df6be,0x3ee63375,0xbf64aa59,0x3ecc9b8b,0xbf6aab7b,0x3eb263ef,0xbf6ff573,0x3e97a117,0xbf748422,
0x3e94a031,0xbf74fa0b,0x3e5a3997,0xbf7a1e84,0x3e09cf86,0xbf7dabcc,0x3d621469,0xbf7f9c18,0xbcc90ab0,0xbf7fec43,0xbdd53db9,0xbf7e9bc9,0xbe3b6ecf,0xbf7baccd,0xbe8586ce,0xbf772417,
0x3f0e39da,0xbf54db31,0x3f00e7e4,0xbf5d2d53,0x3ee63375,0xbf64aa59,0x3ec9b953,0xbf6b4b0c,0x3eac7cd4,0xbf710908,0x3e8e9a22,0xbf75dec6,0x3e605c13,0xbf79c79d,0x3e22abb6,0xbf7cbfc9,
0x3e47c5c2,0xbf7b14be,0x3de1bc2e,0xbf7e70b0,0x3cc90ab0,0xbf7fec43,0xbd7b2b74,0xbf7f84ab,0xbe164083,0xbf7d3aac,0xbe6c9a7f,0xbf791298,0xbea09ae5,0xbf731447,0xbec9b953,0xbf6b4b0c,
0x3ef15aea,0xbf61c598,0x3ed25a09,0xbf696591,0x3eb263ef,0xbf6ff573,0x3e919ddd,0xbf756d97,0x3e605c13,0xbf79c79d,0x3e1c76de,0xbf7cfe73,0x3dafb680,0xbf7f0e58,0x3c96c9b6,0xbf7ff4e6,
0x3dc8bd36,0xbf7ec46d,0x3bc90f88,0xbf7ffec4,0xbdafb680,0xbf7f0e58,0xbe354098,0xbf7bf531,0xbe888e93,0xbf76ba07,0xbeb554ec,0xbf6f6830,0xbee0924f,0xbf660f88,0xbf04f484,0xbf5ac450,
0x0,0xbf800000,0xbdc8bd36,0xbf7ec46d,0xbe47c5c2,0xbf7b14be,0xbe94a031,0xbf74fa0b,0xbec3ef15,0xbf6c835e,0xbef15aea,0xbf61c598,0xbf0e39da,0xbf54db31,0xbf226799,0xbf45e403,
0xbec3ef15,0xbf6c835e,0xbefc5d27,0xbf5ebe05,0xbf187fc0,0xbf4d9f02,0xbf3085bb,0xbf396842,0xbf45e403,0xbf226799,0xbf584853,0xbf08f59b,0xbf676bd8,0xbedae880,0xbf731447,0xbea09ae5,
0xbdc8bd36,0xbf7ec46d,0xbe4dee60,0xbf7ac516,0xbe9aa086,0xbf740bdd,0xbecc9b8b,0xbf6aab7b,0xbefc5d27,0xbf5ebe05,0xbf14b039,0xbf5064af,0xbf299415,0xbf3fc767,0xbf3ca003,0xbf2d1469,
0xbef15aea,0xbf61c598,0xbf14b039,0xbf5064af,0xbf2e3bde,0xbf3b8f3b,0xbf44e3f5,0xbf239da9,0xbf584853,0xbf08f59b,0xbf6816a8,0xbed8106b,0xbf740bdd,0xbe9aa086,0xbf7bf531,0xbe354098,
0xbe47c5c2,0xbf7b14be,0xbe9aa086,0xbf740bdd,0xbecf7bca,0xbf6a09a7,0xbf00e7e4,0xbf5d2d53,0xbf187fc0,0xbf4d9f02,0xbf2e3bde,0xbf3b8f3b,0xbf41d870,0xbf273656,0xbf531849,0xbf10d3cd,
0xbf0e39da,0xbf54db31,0xbf299415,0xbf3fc767,0xbf41d870,0xbf273656,0xbf5695e5,0xbf0b9a6b,0xbf676bd8,0xbedae880,0xbf740bdd,0xbe9aa086,0xbf7c3b28,0xbe2f10a2,0xbf7fd397,0xbd16c32c,
0xbe94a031,0xbf74fa0b,0xbecc9b8b,0xbf6aab7b,0xbf00e7e4,0xbf5d2d53,0xbf19c200,0xbf4cae79,0xbf3085bb,0xbf396842,0xbf44e3f5,0xbf239da9,0xbf5695e5,0xbf0b9a6b,0xbf655e0b,0xbee363fa,
0xbf226799,0xbf45e403,0xbf3ca003,0xbf2d1469,0xbf531849,0xbf10d3cd,0xbf655e0b,0xbee363fa,0xbf731447,0xbea09ae5,0xbf7bf531,0xbe354098,0xbf7fd397,0xbd16c32c,0xbf7e9bc9,0x3dd53db9,
0xbf3504f3,0xbf3504f3,0xbf4d9f02,0xbf187fc0,0xbf61c598,0xbef15aea,0xbf710908,0xbeac7cd4,0xbf7b14be,0xbe47c5c2,0xbf7fb10f,0xbd48fb30,0xbf7ec46d,0x3dc8bd36,0xbf7853f8,0x3e78cfcc,
0xbf6c835e,0xbec3ef15,0xbf79c79d,0xbe605c13,0xbf7fb10f,0xbd48fb30,0xbf7e1324,0x3dfab273,0xbf74fa0b,0x3e94a031,0xbf64aa59,0x3ee63375,0xbf4d9f02,0x3f187fc0,0xbf3085bb,0x3f396842,
0xbf45e403,0xbf226799,0xbf5c61c7,0xbf0242b1,0xbf6db293,0xbebe1d4a,0xbf796e4e,0xbe667c66,0xbf7f4e6d,0xbd96a905,0xbf7f2f9d,0x3da3308c,0xbf791298,0x3e6c9a7f,0xbf6d1c1d,0x3ec1071e,
0xbf74fa0b,0xbe94a031,0xbf7e4323,0xbdee3876,0xbf7f84ab,0x3d7b2b74,0xbf78b47b,0x3e72b651,0xbf6a09a7,0x3ecf7bca,0xbf53fac3,0x3f0f8784,0xbf373a23,0x3f32c8c9,0xbf14b039,0x3f5064af,
0xbf54db31,0xbf0e39da,0xbf68bf3c,0xbed53641,0xbf76ba07,0xbe888e93,0xbf7e70b0,0xbde1bc2e,0xbf7fb10f,0x3d48fb30,0xbf7a7302,0x3e541501,0xbf6ed89e,0x3eb8442a,0xbf5d2d53,0x3f00e7e4,
0xbf7b14be,0xbe47c5c2,0xbf7ffb11,0xbc490e90,0xbf7c3b28,0x3e2f10a2,0xbf6ff573,0x3eb263ef,0xbf5b941a,0x3f039c3d,0xbf3fc767,0x3f299415,0xbf1d7fd1,0x3f49d112,0xbeebcbbb,0x3f633c5a,
0xbf61c598,0xbef15aea,0xbf7294f8,0xbea395c5,0xbf7cbfc9,0xbe22abb6,0xbf7ffec4,0x3bc90f88,0xbf7c3b28,0x3e2f10a2,0xbf718f57,0x3ea986c4,0xbf604621,0x3ef6e0cb,0xbf48d8b3,0x3f1ebc12,
0xbf7ec46d,0xbdc8bd36,0xbf7eea9d,0x3dbc3ac3,0xbf75dec6,0x3e8e9a22,0xbf63f473,0x3ee900b7,0xbf49d112,0x3f1d7fd1,0xbf286605,0x3f40d0da,0xbf00e7e4,0x3f5d2d53,0xbea986c4,0x3f718f57,
0x3f800000,0x0,0x3f800000,0x0,0x3f800000,0x0,0x3f800000,0x0,0x3f800000,0x0,0x3f800000,0x0,0x3f800000,0x0,0x3f800000,0x0,
0x3f54db31,0xbf0e39da,0x3f514d3d,0xbf13682a,0x3f4d9f02,0xbf187fc0,0x3f49d112,0xbf1d7fd1,0x3f45e403,0xbf226799,0x3f41d870,0xbf273656,0x3f3daef9,0xbf2beb4a,0x3f396842,0xbf3085bb,
0x3f7d3aac,0xbe164083,0x3f7cfe73,0xbe1c76de,0x3f7cbfc9,0xbe22abb6,0x3f7c7eb0,0xbe28defc,0x3f7c3b28,0xbe2f10a2,0x3f7bf531,0xbe354098,0x3f7baccd,0xbe3b6ecf,0x3f7b61fc,0xbe419b37,
0x3f3daef9,0xbf2beb4a,0x3f385216,0xbf31a81d,0x3f32c8c9,0xbf373a23,0x3f2d1469,0xbf3ca003,0x3f273656,0xbf41d870,0x3f212ff9,0xbf46e22a,0x3f1b02c6,0xbf4bbbf8,0x3f14b039,0xbf5064af,
0x3f74fa0b,0xbe94a031,0x3f740bdd,0xbe9aa086,0x3f731447,0xbea09ae5,0x3f721352,0xbea68f12,0x3f710908,0xbeac7cd4,0x3f6ff573,0xbeb263ef,0x3f6ed89e,0xbeb8442a,0x3f6db293,0xbebe1d4a,
0x3f226799,0xbf45e403,0x3f1b02c6,0xbf4bbbf8,0x3f13682a,0xbf514d3d,0x3f0b9a6b,0xbf5695e5,0x3f039c3d,0xbf5b941a,0x3ef6e0cb,0xbf604621,0x3ee63375,0xbf64aa59,0x3ed53641,0xbf68bf3c,
0x3f676bd8,0xbedae880,0x3f655e0b,0xbee363fa,0x3f633c5a,0xbeebcbbb,0x3f6106f2,0xbef41f07,0x3f5ebe05,0xbefc5d27,0x3f5c61c7,0xbf0242b1,0x3f59f26a,0xbf064b82,0x3f577026,0xbf0a48ad,
0x3f039c3d,0xbf5b941a,0x3ef41f07,0xbf6106f2,0x3ee0924f,0xbf660f88,0x3ecc9b8b,0xbf6aab7b,0x3eb8442a,0xbf6ed89e,0x3ea395c5,0xbf7294f8,0x3e8e9a22,0xbf75dec6,0x3e72b651,0xbf78b47b,
0x3ec3ef15,0xbf6c835e,0x3eac7cd4,0xbf710908,0x3e94a031,0xbf74fa0b,0x3e78cfcc,0xbf7853f8,0x3e47c5c2,0xbf7b14be,0x3e164083,0xbf7d3aac,0x3dc8bd36,0xbf7ec46d,0x3d48fb30,0xbf7fb10f,
0xbe47c5c2,0xbf7b14be,0xbe888e93,0xbf76ba07,0xbeac7cd4,0xbf710908,0xbecf7bca,0xbf6a09a7,0xbef15aea,0xbf61c598,0xbf08f59b,0xbf584853,0xbf187fc0,0xbf4d9f02,0xbf273656,0xbf41d870,
0x3e78cfcc,0xbf7853f8,0x3e419b37,0xbf7b61fc,0x3e09cf86,0xbf7dabcc,0x3da3308c,0xbf7f2f9d,0x3cc90ab0,0xbf7fec43,0xbcfb49ba,0xbf7fe129,0xbdafb680,0xbf7f0e58,0xbe1008b7,0xbf7d7474,
0xbeac7cd4,0xbf710908,0xbed25a09,0xbf696591,0xbef6e0cb,0xbf604621,0xbf0cead0,0xbf55b993,0xbf1d7fd1,0xbf49d112,0xbf2d1469,0xbf3ca003,0xbf3b8f3b,0xbf2e3bde,0xbf48d8b3,0xbf1ebc12,
0x3dc8bd36,0xbf7ec46d,0x3d16c32c,0xbf7fd397,0xbcc90ab0,0xbf7fec43,0xbdafb680,0xbf7f0e58,0xbe164083,0xbf7d3aac,0xbe541501,0xbf7a7302,0xbe888e93,0xbf76ba07,0xbea68f12,0xbf721352,
0xbef15aea,0xbf61c598,0xbf0b9a6b,0xbf5695e5,0xbf1d7fd1,0xbf49d112,0xbf2e3bde,0xbf3b8f3b,0xbf3daef9,0xbf2beb4a,0xbf4bbbf8,0xbf1b02c6,0xbf584853,0xbf08f59b,0xbf633c5a,0xbeebcbbb,
0xbd48fb30,0xbf7fb10f,0xbdee3876,0xbf7e4323,0xbe3b6ecf,0xbf7baccd,0xbe7ee6e1,0xbf77f110,0xbea09ae5,0xbf731447,0xbec1071e,0xbf6d1c1d,0xbee0924f,0xbf660f88,0xbeff17b2,0xbf5df6be,
0xbf187fc0,0xbf4d9f02,0xbf2ac082,0xbf3ebc1b,0xbf3b8f3b,0xbf2e3bde,0xbf4ac77f,0xbf1c420c,0xbf584853,0xbf08f59b,0xbf63f473,0xbee900b7,0xbf6db293,0xbebe1d4a,0xbf756d97,0xbe919ddd,
0xbf3504f3,0xbf3504f3,0xbf45e403,0xbf226799,0xbf54db31,0xbf0e39da,0xbf61c598,0xbef15aea,0xbf6c835e,0xbec3ef15,0xbf74fa0b,0xbe94a031,0xbf7b14be,0xbe47c5c2,0xbf7ec46d,0xbdc8bd36,
0xbf7b14be,0xbe47c5c2,0xbf7f4e6d,0xbd96a905,0xbf7fb10f,0x3d48fb30,0xbf7c3b28,0x3e2f10a2,0xbf74fa0b,0x3e94a031,0xbf6a09a7,0x3ecf7bca,0xbf5b941a,0x3f039c3d,0xbf49d112,0x3f1d7fd1,
0xbf4d9f02,0xbf187fc0,0xbf5c61c7,0xbf0242b1,0xbf68bf3c,0xbed53641,0xbf7294f8,0xbea395c5,0xbf79c79d,0xbe605c13,0xbf7e4323,0xbdee3876,0xbf7ffb11,0xbc490e90,0xbf7eea9d,0x3dbc3ac3,
0xbf7fb10f,0xbd48fb30,0xbf7f2f9d,0x3da3308c,0xbf7a7302,0x3e541501,0xbf718f57,0x3ea986c4,0xbf64aa59,0x3ee63375,0xbf53fac3,0x3f0f8784,0xbf3fc767,0x3f299415,0xbf286605,0x3f40d0da,
0xbf61c598,0xbef15aea,0xbf6db293,0xbebe1d4a,0xbf76ba07,0xbe888e93,0xbf7cbfc9,0xbe22abb6,0xbf7fb10f,0xbd48fb30,0xbf7f84ab,0x3d7b2b74,0xbf7c3b28,0x3e2f10a2,0xbf75dec6,0x3e8e9a22,
0xbf7ec46d,0x3dc8bd36,0xbf791298,0x3e6c9a7f,0xbf6ed89e,0x3eb8442a,0xbf604621,0x3ef6e0cb,0xbf4d9f02,0x3f187fc0,0xbf373a23,0x3f32c8c9,0xbf1d7fd1,0x3f49d112,0xbf00e7e4,0x3f5d2d53,
0xbf710908,0xbeac7cd4,0xbf796e4e,0xbe667c66,0xbf7e70b0,0xbde1bc2e,0xbf7ffec4,0x3bc90f88,0xbf7e1324,0x3dfab273,0xbf78b47b,0x3e72b651,0xbf6ff573,0x3eb263ef,0xbf63f473,0x3ee900b7,
0xbf7853f8,0x3e78cfcc,0xbf6d1c1d,0x3ec1071e,0xbf5d2d53,0x3f00e7e4,0xbf48d8b3,0x3f1ebc12,0xbf3085bb,0x3f396842,0xbf14b039,0x3f5064af,0xbeebcbbb,0x3f633c5a,0xbea986c4,0x3f718f57,
0xbf6c835e,0x3ec3ef15,0xbf5b941a,0x3f039c3d,0xbf45e403,0x3f226799,0xbf2beb4a,0x3f3daef9,0xbf0e39da,0x3f54db31,0xbedae880,0x3f676bd8,0xbe94a031,0x3f74fa0b,0xbe164083,0x3f7d3aac,
0xbf0e39da,0x3f54db31,0xbecf7bca,0x3f6a09a7,0xbe78cfcc,0x3f7853f8,0xbd96a905,0x3f7f4e6d,0x3dc8bd36,0x3f7ec46d,0x3e888e93,0x3f76ba07,0x3edae880,0x3f676bd8,0x3f13682a,0x3f514d3d,
0xbf5b941a,0x3f039c3d,0xbf44e3f5,0x3f239da9,0xbf299415,0x3f3fc767,0xbf0a48ad,0x3f577026,0xbecf7bca,0x3f6a09a7,0xbe8586ce,0x3f772417,0xbde1bc2e,0x3f7e70b0,0x3d2fe007,0x3f7fc38f,
0xbedae880,0x3f676bd8,0xbe8586ce,0x3f772417,0xbdafb680,0x3f7f0e58,0x3dbc3ac3,0x3f7eea9d,0x3e888e93,0x3f76ba07,0x3eddbe79,0x3f66becc,0x3f15f6d9,0x3f4f7a1f,0x3f385216,0x3f31a81d,
0xbf45e403,0x3f226799,0xbf299415,0x3f3fc767,0xbf08f59b,0x3f584853,0xbec9b953,0x3f6b4b0c,0xbe78cfcc,0x3f7853f8,0xbdafb680,0x3f7f0e58,0x3d96a905,0x3f7f4e6d,0x3e6c9a7f,0x3f791298,
0xbe94a031,0x3f74fa0b,0xbde1bc2e,0x3f7e70b0,0x3d96a905,0x3f7f4e6d,0x3e827dc0,0x3f778bc5,0x3edae880,0x3f676bd8,0x3f15f6d9,0x3f4f7a1f,0x3f396842,0x3f3085bb,0x3f5695e5,0x3f0b9a6b,
0xbf2beb4a,0x3f3daef9,0xbf0a48ad,0x3f577026,0xbec9b953,0x3f6b4b0c,0xbe72b651,0x3f78b47b,0xbd96a905,0x3f7f4e6d,0x3dbc3ac3,0x3f7eea9d,0x3e827dc0,0x3f778bc5,0x3ed25a09,0x3f696591,
0xbe164083,0x3f7d3aac,0x3d2fe007,0x3f7fc38f,0x3e6c9a7f,0x3f791298,0x3ed25a09,0x3f696591,0x3f13682a,0x3f514d3d,0x3f385216,0x3f31a81d,0x3f5695e5,0x3f0b9a6b,0x3f6d1c1d,0x3ec1071e,
0x3e00,0x3e00,0x3e00,0x3e00,0x3e00,0x3e00,0x3e00,0x3e00,0x3e00,0x3e00,0x3e00,0x3e00,0x3e00,0x3e00,0x3e00,0x3e00,
0xbd443ded,0xbcc83dfb,0xbc493dff,0xbd153df5,0xbdb53db5,0xbdd53d8e,0xbdc63da2,0xbde23d71,0xbe000000,0xbdfbbcc8,0xbdffbc49,0xbdf5bd15,0xbdb5bdb5,0xbd8ebdd5,0xbda2bdc6,0xbd71bde2,
0xbdb53db5,0xbd443ded,0xbcc83dfb,0xbd8e3dd5,0xbe000000,0xbdedbd44,0xbdfbbcc8,0xbdd5bd8e,0xbe00,0x3d44bded,0x3cc8bdfb,0x3d8ebdd5,0x3e000000,0x3ded3d44,0x3dfb3cc8,0x3dd53d8e,
0xbded3d44,0xbd8e3dd5,0xbd153df5,0xbdc63da2,0xbdb5bdb5,0xbcc8bdfb,0xbd71bde2,0x3c49bdff,0x3e000000,0x3dd53d8e,0x3df53d15,0x3da23dc6,0xbdb53db5,0xbdfb3cc8,0xbde23d71,0xbdffbc49,
0xbe000000,0xbdb53db5,0xbd443ded,0xbded3d44,0xbe00,0x3db5bdb5,0x3d44bded,0x3dedbd44,0x3e00,0xbdb53db5,0xbd443ded,0xbded3d44,0xbe00,0x3db5bdb5,0x3d44bded,0x3dedbd44,
0xbdedbd44,0xbdd53d8e,0xbd713de2,0xbdff3c49,0x3db5bdb5,0x3dfb3cc8,0x3df5bd15,0x3dc63da2,0xbe000000,0xbd8ebdd5,0xbde2bd71,0xbc49bdff,0x3db53db5,0xbcc83dfb,0x3d153df5,0xbda23dc6,
0xbdb5bdb5,0xbded3d44,0xbd8e3dd5,0xbdfbbcc8,0x3e000000,0x3d443ded,0x3dd53d8e,0xbcc83dfb,0xbe00,0x3dedbd44,0x3d8ebdd5,0x3dfb3cc8,0xbe000000,0xbd44bded,0xbdd5bd8e,0x3cc8bdfb,
0xbd44bded,0xbdfb3cc8,0xbda23dc6,0xbde2bd71,0x3db53db5,0xbd8e3dd5,0x3c493dff,0xbdf53d15,0x3e000000,0x3cc83dfb,0x3dc63da2,0xbd713de2,0x3db5bdb5,0x3dd53d8e,0x3dffbc49,0x3d153df5,
0xbe00,0xbe000000,0xbdb53db5,0xbdb5bdb5,0x3e00,0xbe000000,0xbdb53db5,0xbdb5bdb5,0x3e00,0xbe000000,0xbdb53db5,0xbdb5bdb5,0x3e00,0xbe000000,0xbdb53db5,0xbdb5bdb5,
0x3d44bded,0xbdfbbcc8,0xbdc63da2,0xbd71bde2,0xbdb53db5,0xbd8ebdd5,0xbdffbc49,0x3d15bdf5,0xbe000000,0x3cc8bdfb,0xbda2bdc6,0x3de2bd71,0xbdb5bdb5,0x3dd5bd8e,0x3c49bdff,0x3df53d15,
0x3db5bdb5,0xbdedbd44,0xbdd53d8e,0xbcc8bdfb,0xbe000000,0x3d44bded,0xbd8ebdd5,0x3dfbbcc8,0xbe00,0x3ded3d44,0x3dd5bd8e,0x3cc83dfb,0x3e000000,0xbd443ded,0x3d8e3dd5,0xbdfb3cc8,
0x3dedbd44,0xbdd5bd8e,0xbde23d71,0x3c49bdff,0xbdb5bdb5,0x3dfbbcc8,0x3d15bdf5,0x3da23dc6,0x3e000000,0xbd8e3dd5,0x3d713de2,0xbdffbc49,0xbdb53db5,0xbcc8bdfb,0xbdf5bd15,0x3dc6bda2,
0x3e000000,0xbdb5bdb5,0xbded3d44,0x3d44bded,0xbe00,0x3db53db5,0x3dedbd44,0xbd443ded,0x3e00,0xbdb5bdb5,0xbded3d44,0x3d44bded,0xbe00,0x3db53db5,0x3dedbd44,0xbd443ded,
0x3ded3d44,0xbd8ebdd5,0xbdf53d15,0x3da2bdc6,0x3db5bdb5,0xbcc83dfb,0x3de23d71,0xbdff3c49,0xbe000000,0x3dd5bd8e,0xbd15bdf5,0x3dc63da2,0x3db53db5,0xbdfbbcc8,0xbd713de2,0xbc49bdff,
0x3db53db5,0xbd44bded,0xbdfb3cc8,0x3dd5bd8e,0x3e000000,0xbded3d44,0x3cc83dfb,0xbd8ebdd5,0xbe00,0x3d443ded,0x3dfbbcc8,0xbdd53d8e,0xbe000000,0x3dedbd44,0xbcc8bdfb,0x3d8e3dd5,
0x3d443ded,0xbcc8bdfb,0xbdff3c49,0x3df5bd15,0x3db53db5,0xbdd5bd8e,0xbda23dc6,0x3d71bde2,0x3e000000,0xbdfb3cc8,0x3c493dff,0xbd15bdf5,0x3db5bdb5,0xbd8e3dd5,0x3dc63da2,0xbde2bd71,
0x3e00,0xbe00,0xbe000000,0x3e000000,0x3e00,0xbe00,0xbe000000,0x3e000000,0x3e00,0xbe00,0xbe000000,0x3e000000,0x3e00,0xbe00,0xbe000000,0x3e000000,
0xbd443ded,0x3cc8bdfb,0xbdffbc49,0x3df53d15,0xbdb53db5,0x3dd5bd8e,0xbda2bdc6,0x3d713de2,0xbe000000,0x3dfb3cc8,0x3c49bdff,0xbd153df5,0xbdb5bdb5,0x3d8e3dd5,0x3dc6bda2,0xbde23d71,
0xbdb53db5,0x3d44bded,0xbdfbbcc8,0x3dd53d8e,0xbe000000,0x3ded3d44,0x3cc8bdfb,0xbd8e3dd5,0xbe00,0xbd443ded,0x3dfb3cc8,0xbdd5bd8e,0x3e000000,0xbdedbd44,0xbcc83dfb,0x3d8ebdd5,
0xbded3d44,0x3d8ebdd5,0xbdf5bd15,0x3da23dc6,0xbdb5bdb5,0x3cc83dfb,0x3de2bd71,0xbdffbc49,0x3e000000,0xbdd5bd8e,0xbd153df5,0x3dc6bda2,0xbdb53db5,0x3dfbbcc8,0xbd71bde2,0xbc493dff,
0xbe000000,0x3db5bdb5,0xbdedbd44,0x3d443ded,0xbe00,0xbdb53db5,0x3ded3d44,0xbd44bded,0x3e00,0x3db5bdb5,0xbdedbd44,0x3d443ded,0xbe00,0xbdb53db5,0x3ded3d44,0xbd44bded,
0xbdedbd44,0x3dd5bd8e,0xbde2bd71,0x3c493dff,0x3db5bdb5,0xbdfbbcc8,0x3d153df5,0x3da2bdc6,0xbe000000,0x3d8e3dd5,0x3d71bde2,0xbdff3c49,0x3db53db5,0x3cc8bdfb,0xbdf53d15,0x3dc63da2,
0xbdb5bdb5,0x3dedbd44,0xbdd5bd8e,0xbcc83dfb,0x3e000000,0xbd44bded,0xbd8e3dd5,0x3dfb3cc8,0xbe00,0xbded3d44,0x3dd53d8e,0x3cc8bdfb,0xbe000000,0x3d443ded,0x3d8ebdd5,0xbdfbbcc8,
0xbd44bded,0x3dfbbcc8,0xbdc6bda2,0xbd713de2,0x3db53db5,0x3d8ebdd5,0xbdff3c49,0x3d153df5,0x3e000000,0xbcc8bdfb,0xbda23dc6,0x3de23d71,0x3db5bdb5,0xbdd5bd8e,0x3c493dff,0x3df5bd15,
0xbe00,0x3e000000,0xbdb5bdb5,0xbdb53db5,0x3e00,0x3e000000,0xbdb5bdb5,0xbdb53db5,0x3e00,0x3e000000,0xbdb5bdb5,0xbdb53db5,0x3e00,0x3e000000,0xbdb5bdb5,0xbdb53db5,
0x3d44bded,0x3dfb3cc8,0xbda2bdc6,0xbde23d71,0xbdb53db5,0x3d8e3dd5,0x3c49bdff,0xbdf5bd15,0xbe000000,0xbcc83dfb,0x3dc6bda2,0xbd71bde2,0xbdb5bdb5,0xbdd53d8e,0x3dff3c49,0x3d15bdf5,
0x3db5bdb5,0x3ded3d44,0xbd8ebdd5,0xbdfb3cc8,0xbe000000,0xbd443ded,0x3dd5bd8e,0xbcc8bdfb,0xbe00,0xbdedbd44,0x3d8e3dd5,0x3dfbbcc8,0x3e000000,0x3d44bded,0xbdd53d8e,0x3cc83dfb,
0x3dedbd44,0x3dd53d8e,0xbd71bde2,0xbdffbc49,0xbdb5bdb5,0xbdfb3cc8,0x3df53d15,0x3dc6bda2,0x3e000000,0x3d8ebdd5,0xbde23d71,0xbc493dff,0xbdb53db5,0x3cc83dfb,0x3d15bdf5,0xbda2bdc6,
0x3e000000,0x3db53db5,0xbd44bded,0xbdedbd44,0xbe00,0xbdb5bdb5,0x3d443ded,0x3ded3d44,0x3e00,0x3db53db5,0xbd44bded,0xbdedbd44,0xbe00,0xbdb5bdb5,0x3d443ded,0x3ded3d44,
0x3ded3d44,0x3d8e3dd5,0xbd15bdf5,0xbdc6bda2,0x3db5bdb5,0x3cc8bdfb,0xbd713de2,0x3c493dff,0xbe000000,0xbdd53d8e,0x3df5bd15,0x3da2bdc6,0x3db53db5,0x3dfb3cc8,0xbde2bd71,0xbdff3c49,
0x3db53db5,0x3d443ded,0xbcc8bdfb,0xbd8ebdd5,0x3e000000,0x3dedbd44,0xbdfb3cc8,0xbdd53d8e,0xbe00,0xbd44bded,0x3cc83dfb,0x3d8e3dd5,0xbe000000,0xbded3d44,0x3dfbbcc8,0x3dd5bd8e,
0x3d443ded,0x3cc83dfb,0xbc49bdff,0xbd15bdf5,0x3db53db5,0x3dd53d8e,0xbdc6bda2,0xbde2bd71,0x3e000000,0x3dfbbcc8,0xbdff3c49,0xbdf53d15,0x3db5bdb5,0x3d8ebdd5,0xbda23dc6,0xbd713de2,
0x3d803d80,0x3e00,0x3e00,0x3e00,0x3e00,0x3e00,0x3e00,0x3e00,0x3e00,0x3e00,0x3e00,0x3e00,0x3e00,0x3e00,0x3e00,0x3e00,
0xbd803d80,0x3cc8bdfb,0x3c49bdff,0x3d15bdf5,0xbded3d44,0x3dd5bd8e,0x3dc6bda2,0x3de2bd71,0xbdedbd44,0x3dfb3cc8,0x3dff3c49,0x3df53d15,0xbd44bded,0x3d8e3dd5,0x3da23dc6,0x3d713de2,
0x3d803d80,0xbd443ded,0xbcc83dfb,0xbd8e3dd5,0xbdb5bdb5,0xbdedbd44,0xbdfbbcc8,0xbdd5bd8e,0x3db5bdb5,0x3d44bded,0x3cc8bdfb,0x3d8ebdd5,0x3db53db5,0x3ded3d44,0x3dfb3cc8,0x3dd53d8e,
0xbd803d80,0x3d8ebdd5,0x3d15bdf5,0x3dc6bda2,0x3d44bded,0x3cc83dfb,0x3d713de2,0xbc493dff,0x3d443ded,0xbdd5bd8e,0xbdf5bd15,0xbda2bdc6,0xbdedbd44,0x3dfbbcc8,0x3de2bd71,0x3dff3c49,
0x3d803d80,0xbdb53db5,0xbd443ded,0xbded3d44,0x3e000000,0x3db5bdb5,0x3d44bded,0x3dedbd44,0xbe000000,0xbdb53db5,0xbd443ded,0xbded3d44,0x3e000000,0x3db5bdb5,0x3d44bded,0x3dedbd44,
0xbd803d80,0x3dd5bd8e,0x3d71bde2,0x3dffbc49,0x3d443ded,0xbdfbbcc8,0xbdf53d15,0xbdc6bda2,0x3d44bded,0x3d8e3dd5,0x3de23d71,0x3c493dff,0xbded3d44,0x3cc8bdfb,0xbd15bdf5,0x3da2bdc6,
0x3d803d80,0xbded3d44,0xbd8e3dd5,0xbdfbbcc8,0xbdb53db5,0x3d443ded,0x3dd53d8e,0xbcc83dfb,0x3db53db5,0x3dedbd44,0x3d8ebdd5,0x3dfb3cc8,0x3db5bdb5,0xbd44bded,0xbdd5bd8e,0x3cc8bdfb,
0xbd803d80,0x3dfbbcc8,0x3da2bdc6,0x3de23d71,0xbdedbd44,0x3d8ebdd5,0xbc49bdff,0x3df5bd15,0xbded3d44,0xbcc8bdfb,0xbdc6bda2,0x3d71bde2,0xbd443ded,0xbdd5bd8e,0xbdff3c49,0xbd15bdf5,
0x3d803d80,0xbe000000,0xbdb53db5,0xbdb5bdb5,0xbe00,0xbe000000,0xbdb53db5,0xbdb5bdb5,0xbe00,0xbe000000,0xbdb53db5,0xbdb5bdb5,0xbe00,0xbe000000,0xbdb53db5,0xbdb5bdb5,
0xbd803d80,0x3dfb3cc8,0x3dc6bda2,0x3d713de2,0x3dedbd44,0x3d8e3dd5,0x3dff3c49,0xbd153df5,0x3ded3d44,0xbcc83dfb,0x3da23dc6,0xbde23d71,0x3d443ded,0xbdd53d8e,0xbc493dff,0xbdf5bd15,
0x3d803d80,0xbdedbd44,0xbdd53d8e,0xbcc8bdfb,0x3db53db5,0x3d44bded,0xbd8ebdd5,0x3dfbbcc8,0xbdb53db5,0x3ded3d44,0x3dd5bd8e,0x3cc83dfb,0xbdb5bdb5,0xbd443ded,0x3d8e3dd5,0xbdfb3cc8,
0xbd803d80,0x3dd53d8e,0x3de2bd71,0xbc493dff,0xbd443ded,0xbdfb3cc8,0xbd153df5,0xbda2bdc6,0xbd44bded,0x3d8ebdd5,0xbd71bde2,0x3dff3c49,0x3ded3d44,0x3cc83dfb,0x3df53d15,0xbdc63da2,
0x3d803d80,0xbdb5bdb5,0xbded3d44,0x3d44bded,0xbe000000,0x3db53db5,0x3dedbd44,0xbd443ded,0x3e000000,0xbdb5bdb5,0xbded3d44,0x3d44bded,0xbe000000,0x3db53db5,0x3dedbd44,0xbd443ded,
0xbd803d80,0x3d8e3dd5,0x3df5bd15,0xbda23dc6,0xbd44bded,0x3cc8bdfb,0xbde2bd71,0x3dffbc49,0xbd443ded,0xbdd53d8e,0x3d153df5,0xbdc6bda2,0x3dedbd44,0x3dfb3cc8,0x3d71bde2,0x3c493dff,
0x3d803d80,0xbd44bded,0xbdfb3cc8,0x3dd5bd8e,0x3db5bdb5,0xbded3d44,0x3cc83dfb,0xbd8ebdd5,0xbdb5bdb5,0x3d443ded,0x3dfbbcc8,0xbdd53d8e,0xbdb53db5,0x3dedbd44,0xbcc8bdfb,0x3d8e3dd5,
0xbd803d80,0x3cc83dfb,0x3dffbc49,0xbdf53d15,0x3ded3d44,0x3dd53d8e,0x3da2bdc6,0xbd713de2,0x3dedbd44,0x3dfbbcc8,0xbc49bdff,0x3d153df5,0x3d44bded,0x3d8ebdd5,0xbdc6bda2,0x3de23d71,
0x3d803d80,0xbe00,0xbe000000,0x3e000000,0x3e00,0xbe00,0xbe000000,0x3e000000,0x3e00,0xbe00,0xbe000000,0x3e000000,0x3e00,0xbe00,0xbe000000,0x3e000000,
0xbd803d80,0xbcc83dfb,0x3dff3c49,0xbdf5bd15,0xbded3d44,0xbdd53d8e,0x3da23dc6,0xbd71bde2,0xbdedbd44,0xbdfbbcc8,0xbc493dff,0x3d15bdf5,0xbd44bded,0xbd8ebdd5,0xbdc63da2,0x3de2bd71,
0x3d803d80,0x3d44bded,0xbdfbbcc8,0x3dd53d8e,0xbdb5bdb5,0x3ded3d44,0x3cc8bdfb,0xbd8e3dd5,0x3db5bdb5,0xbd443ded,0x3dfb3cc8,0xbdd5bd8e,0x3db53db5,0xbdedbd44,0xbcc83dfb,0x3d8ebdd5,
0xbd803d80,0xbd8e3dd5,0x3df53d15,0xbda2bdc6,0x3d44bded,0xbcc8bdfb,0xbde23d71,0x3dff3c49,0x3d443ded,0x3dd53d8e,0x3d15bdf5,0xbdc63da2,0xbdedbd44,0xbdfb3cc8,0x3d713de2,0x3c49bdff,
0x3d803d80,0x3db5bdb5,0xbdedbd44,0x3d443ded,0x3e000000,0xbdb53db5,0x3ded3d44,0xbd44bded,0xbe000000,0x3db5bdb5,0xbdedbd44,0x3d443ded,0x3e000000,0xbdb53db5,0x3ded3d44,0xbd44bded,
0xbd803d80,0xbdd53d8e,0x3de23d71,0xbc49bdff,0x3d443ded,0x3dfb3cc8,0xbd15bdf5,0xbda23dc6,0x3d44bded,0xbd8ebdd5,0xbd713de2,0x3dffbc49,0xbded3d44,0xbcc83dfb,0x3df5bd15,0xbdc6bda2,
0x3d803d80,0x3dedbd44,0xbdd5bd8e,0xbcc83dfb,0xbdb53db5,0xbd44bded,0xbd8e3dd5,0x3dfb3cc8,0x3db53db5,0xbded3d44,0x3dd53d8e,0x3cc8bdfb,0x3db5bdb5,0x3d443ded,0x3d8ebdd5,0xbdfbbcc8,
0xbd803d80,0xbdfb3cc8,0x3dc63da2,0x3d71bde2,0xbdedbd44,0xbd8e3dd5,0x3dffbc49,0xbd15bdf5,0xbded3d44,0x3cc83dfb,0x3da2bdc6,0xbde2bd71,0xbd443ded,0x3dd53d8e,0xbc49bdff,0xbdf53d15,
0x3d803d80,0x3e000000,0xbdb5bdb5,0xbdb53db5,0xbe00,0x3e000000,0xbdb5bdb5,0xbdb53db5,0xbe00,0x3e000000,0xbdb5bdb5,0xbdb53db5,0xbe00,0x3e000000,0xbdb5bdb5,0xbdb53db5,
0xbd803d80,0xbdfbbcc8,0x3da23dc6,0x3de2bd71,0x3dedbd44,0xbd8ebdd5,0xbc493dff,0x3df53d15,0x3ded3d44,0x3cc8bdfb,0xbdc63da2,0x3d713de2,0x3d443ded,0x3dd5bd8e,0xbdffbc49,0xbd153df5,
0x3d803d80,0x3ded3d44,0xbd8ebdd5,0xbdfb3cc8,0x3db53db5,0xbd443ded,0x3dd5bd8e,0xbcc8bdfb,0xbdb53db5,0xbdedbd44,0x3d8e3dd5,0x3dfbbcc8,0xbdb5bdb5,0x3d44bded,0xbdd53d8e,0x3cc83dfb,
0xbd803d80,0xbdd5bd8e,0x3d713de2,0x3dff3c49,0xbd443ded,0x3dfbbcc8,0xbdf5bd15,0xbdc63da2,0xbd44bded,0xbd8e3dd5,0x3de2bd71,0x3c49bdff,0x3ded3d44,0xbcc8bdfb,0xbd153df5,0x3da23dc6,
0x3d803d80,0x3db53db5,0xbd44bded,0xbdedbd44,0xbe000000,0xbdb5bdb5,0x3d443ded,0x3ded3d44,0x3e000000,0x3db53db5,0xbd44bded,0xbdedbd44,0xbe000000,0xbdb5bdb5,0x3d443ded,0x3ded3d44,
0xbd803d80,0xbd8ebdd5,0x3d153df5,0x3dc63da2,0xbd44bded,0xbcc83dfb,0x3d71bde2,0xbc49bdff,0xbd443ded,0x3dd5bd8e,0xbdf53d15,0xbda23dc6,0x3dedbd44,0xbdfbbcc8,0x3de23d71,0x3dffbc49,
0x3d803d80,0x3d443ded,0xbcc8bdfb,0xbd8ebdd5,0x3db5bdb5,0x3dedbd44,0xbdfb3cc8,0xbdd53d8e,0xbdb5bdb5,0xbd44bded,0x3cc83dfb,0x3d8e3dd5,0xbdb53db5,0xbded3d44,0x3dfbbcc8,0x3dd5bd8e,
0xbd803d80,0xbcc8bdfb,0x3c493dff,0x3d153df5,0x3ded3d44,0xbdd5bd8e,0x3dc63da2,0x3de23d71,0x3dedbd44,0xbdfb3cc8,0x3dffbc49,0x3df5bd15,0x3d44bded,0xbd8e3dd5,0x3da2bdc6,0x3d71bde2,
0xbc493dff,0xbbc93e00,0xbb493e00,0xbc173dff,0xbcc83dfb,0xbcf93df8,0xbce03dfa,0xbd093df7,0xbd443ded,0xbd5b3de7,0xbd4f3dea,0xbd663de5,0xbd8e3dd5,0xbd983dce,0xbd933dd1,0xbd9d3dca,
0xbd713de2,0xbcf93df8,0xbc7b3dfe,0xbd383def,0xbdd53d8e,0xbdf13d2c,0xbde53d66,0xbdfa3ce0,0xbdedbd44,0xbdcebd98,0xbddfbd7c,0xbdb9bdb1,0xbcc8bdfb,0x3bc9be00,0xbc17bdff,0x3cafbdfc,
0xbdc63da2,0xbd5b3de7,0xbce03dfa,0xbd9d3dca,0xbdfbbcc8,0xbdcebd98,0xbdeabd4f,0xbda7bdc2,0x3d44bded,0x3dbebdac,0x3d93bdd1,0x3ddfbd7c,0x3dd53d8e,0x3d843ddc,0x3db13db9,0x3d213df3,
0xbdf53d15,0xbd983dce,0xbd213df3,0xbdd13d93,0xbd8ebdd5,0x3bc9be00,0xbd09bdf7,0x3d38bdef,0x3ded3d44,0x3d843ddc,0x3dc23da7,0x3ce03dfa,0xbdfb3cc8,0xbde7bd5b,0xbdfebc7b,0xbdb9bdb1,
0xbdffbc49,0xbdbe3dac,0xbd4f3dea,0xbdf33d21,0x3cc8bdfb,0x3ddcbd84,0x3d93bdd1,0x3dfebc7b,0xbd443ded,0xbdf13d2c,0xbdb93db1,0xbdffbc17,0x3d8ebdd5,0x3dfdbc96,0x3dd8bd89,0x3df73d09,
0xbde2bd71,0xbddc3d84,0xbd7c3ddf,0xbe003b49,0x3dd5bd8e,0x3de73d5b,0x3dffbc17,0x3d933dd1,0xbdedbd44,0xbc96bdfd,0xbd9dbdca,0x3d38bdef,0x3cc83dfb,0xbdbe3dac,0xbd213df3,0xbdfa3ce0,
0xbda2bdc6,0xbdf13d2c,0xbd933dd1,0xbdf7bd09,0x3dfb3cc8,0x3c963dfd,0x3db13db9,0xbd663de5,0x3d44bded,0x3e003bc9,0x3dd8bd89,0x3dca3d9d,0xbdd5bd8e,0x3cf9bdf8,0xbd38bdef,0x3dc2bda7,
0xbd15bdf5,0xbdfd3c96,0xbda73dc2,0xbdd8bd89,0x3d8e3dd5,0xbdbe3dac,0xbc7b3dfe,0xbe003b49,0x3ded3d44,0xbcf93df8,0x3d663de5,0xbdd13d93,0x3dfbbcc8,0x3d2c3df1,0x3ddf3d7c,0xbd383def,
0x3c49bdff,0xbe00bbc9,0xbdb93db1,0xbda7bdc2,0xbcc83dfb,0xbdf8bcf9,0xbdd83d89,0xbd7cbddf,0xbd443ded,0xbde7bd5b,0xbdef3d38,0xbd21bdf3,0xbd8e3dd5,0xbdcebd98,0xbdfc3caf,0xbc7bbdfe,
0x3d71bde2,0xbdf8bcf9,0xbdca3d9d,0xbd4fbdea,0xbdd53d8e,0xbd2cbdf1,0xbdf3bd21,0x3d89bdd8,0xbdedbd44,0x3d98bdce,0xbd09bdf7,0x3e00bb49,0xbcc8bdfb,0x3e003bc9,0x3da7bdc2,0x3d933dd1,
0x3dc6bda2,0xbde7bd5b,0xbdd83d89,0xbc7bbdfe,0xbdfbbcc8,0x3d98bdce,0xbd38bdef,0x3dff3c17,0x3d44bded,0x3dac3dbe,0x3dfcbcaf,0xbd093df7,0x3dd53d8e,0xbddc3d84,0xbb493e00,0xbde5bd66,
0x3df5bd15,0xbdcebd98,0xbde53d66,0x3cafbdfc,0xbd8ebdd5,0x3e003bc9,0x3d7cbddf,0x3d4f3dea,0x3ded3d44,0xbddc3d84,0x3c173dff,0xbdd8bd89,0xbdfb3cc8,0x3d5bbde7,0xbd9dbdca,0x3e00bb49,
0x3dff3c49,0xbdacbdbe,0xbdef3d38,0x3d66bde5,0x3cc8bdfb,0x3d843ddc,0x3dfcbcaf,0xbd9d3dca,0xbd443ded,0xbd2cbdf1,0xbe00bb49,0x3dc2bda7,0x3d8ebdd5,0x3c963dfd,0x3dfa3ce0,0xbddf3d7c,
0x3de23d71,0xbd84bddc,0xbdf73d09,0x3db1bdb9,0x3dd5bd8e,0xbd5b3de7,0x3dc23da7,0xbdfcbcaf,0xbdedbd44,0x3dfdbc96,0x3c7bbdfe,0x3d4f3dea,0x3cc83dfb,0xbdacbdbe,0xbde53d66,0x3d89bdd8,
0x3da23dc6,0xbd2cbdf1,0xbdfc3caf,0x3ddfbd7c,0x3dfb3cc8,0xbdfd3c96,0xbb493e00,0xbd21bdf3,0x3d44bded,0xbbc93e00,0x3dfa3ce0,0xbdfe3c7b,0xbdd5bd8e,0x3df83cf9,0x3d4fbdea,0xbc173dff,
0x3d153df5,0xbc96bdfd,0xbdff3c17,0x3dfabce0,0x3d8e3dd5,0xbdacbdbe,0xbdca3d9d,0x3db1bdb9,0x3ded3d44,0xbdf8bcf9,0xbd213df3,0x3cafbdfc,0x3dfbbcc8,0xbdf13d2c,0x3d093df7,0xbd4fbdea,
0xbc493dff,0x3bc9be00,0xbe00bb49,0x3dff3c17,0xbcc83dfb,0x3cf9bdf8,0xbdfabce0,0x3df73d09,0xbd443ded,0x3d5bbde7,0xbdeabd4f,0x3de53d66,0xbd8e3dd5,0x3d98bdce,0xbdd1bd93,0x3dca3d9d,
0xbd713de2,0x3cf9bdf8,0xbdfebc7b,0x3def3d38,0xbdd53d8e,0x3df1bd2c,0xbd66bde5,0x3ce03dfa,0xbdedbd44,0x3dce3d98,0x3d7cbddf,0xbdb13db9,0xbcc8bdfb,0xbbc93e00,0x3dffbc17,0xbdfcbcaf,
0xbdc63da2,0x3d5bbde7,0xbdfabce0,0x3dca3d9d,0xbdfbbcc8,0x3dce3d98,0x3d4fbdea,0xbdc23da7,0x3d44bded,0xbdbe3dac,0x3dd13d93,0xbd7cbddf,0x3dd53d8e,0xbd84bddc,0xbdb93db1,0x3df3bd21,
0xbdf53d15,0x3d98bdce,0xbdf3bd21,0x3d933dd1,0xbd8ebdd5,0xbbc93e00,0x3df7bd09,0xbdefbd38,0x3ded3d44,0xbd84bddc,0xbda73dc2,0x3dfabce0,0xbdfb3cc8,0x3de73d5b,0x3c7bbdfe,0xbdb13db9,
0xbdffbc49,0x3dbebdac,0xbdeabd4f,0x3d213df3,0x3cc8bdfb,0xbddc3d84,0x3dd13d93,0xbc7bbdfe,0xbd443ded,0x3df1bd2c,0xbdb1bdb9,0xbc173dff,0x3d8ebdd5,0xbdfd3c96,0x3d893dd8,0x3d09bdf7,
0xbde2bd71,0x3ddcbd84,0xbddfbd7c,0x3b493e00,0x3dd5bd8e,0xbde7bd5b,0x3c173dff,0x3dd1bd93,0xbdedbd44,0x3c963dfd,0x3dcabd9d,0xbdefbd38,0x3cc83dfb,0x3dbebdac,0xbdf3bd21,0x3ce03dfa,
0xbda2bdc6,0x3df1bd2c,0xbdd1bd93,0xbd093df7,0x3dfb3cc8,0xbc96bdfd,0xbdb93db1,0x3de53d66,0x3d44bded,0xbe00bbc9,0x3d893dd8,0x3d9dbdca,0xbdd5bd8e,0xbcf93df8,0x3defbd38,0xbda7bdc2,
0xbd15bdf5,0x3dfdbc96,0xbdc2bda7,0xbd893dd8,0x3d8e3dd5,0x3dbebdac,0xbdfebc7b,0x3b493e00,0x3ded3d44,0x3cf9bdf8,0xbde53d66,0x3d933dd1,0x3dfbbcc8,0xbd2cbdf1,0xbd7c3ddf,0x3def3d38,
0x3c49bdff,0x3e003bc9,0xbdb1bdb9,0xbdc23da7,0xbcc83dfb,0x3df83cf9,0xbd89bdd8,0xbddf3d7c,0xbd443ded,0x3de73d5b,0xbd38bdef,0xbdf33d21,0xbd8e3dd5,0x3dce3d98,0xbcafbdfc,0xbdfe3c7b,
0x3d71bde2,0x3df83cf9,0xbd9dbdca,0xbdea3d4f,0xbdd53d8e,0x3d2c3df1,0x3d21bdf3,0xbdd8bd89,0xbdedbd44,0xbd983dce,0x3df7bd09,0xbb49be00,0xbcc8bdfb,0xbe00bbc9,0x3dc23da7,0x3dd1bd93,
0x3dc6bda2,0x3de73d5b,0xbd89bdd8,0xbdfe3c7b,0xbdfbbcc8,0xbd983dce,0x3defbd38,0x3c17bdff,0x3d44bded,0xbdacbdbe,0x3caf3dfc,0x3df73d09,0x3dd53d8e,0x3ddcbd84,0xbe00bb49,0xbd663de5,
0x3df5bd15,0x3dce3d98,0xbd66bde5,0xbdfcbcaf,0xbd8ebdd5,0xbe00bbc9,0x3ddf3d7c,0x3deabd4f,0x3ded3d44,0x3ddcbd84,0xbdff3c17,0xbd893dd8,0xbdfb3cc8,0xbd5b3de7,0x3dcabd9d,0xbb49be00,
0x3dff3c49,0x3dac3dbe,0xbd38bdef,0xbde5bd66,0x3cc8bdfb,0xbd84bddc,0x3caf3dfc,0x3dca3d9d,0xbd443ded,0x3d2c3df1,0x3b49be00,0xbda7bdc2,0x3d8ebdd5,0xbc96bdfd,0xbce03dfa,0x3d7c3ddf,
0x3de23d71,0x3d843ddc,0xbd09bdf7,0xbdb9bdb1,0x3dd5bd8e,0x3d5bbde7,0xbda73dc2,0xbcaf3dfc,0xbdedbd44,0xbdfd3c96,0x3dfe3c7b,0x3deabd4f,0x3cc83dfb,0x3dac3dbe,0xbd66bde5,0xbdd8bd89,
0x3da23dc6,0x3d2c3df1,0xbcafbdfc,0xbd7cbddf,0x3dfb3cc8,0x3dfdbc96,0xbe00bb49,0xbdf33d21,0x3d44bded,0x3bc9be00,0xbce03dfa,0x3c7b3dfe,0xbdd5bd8e,0xbdf8bcf9,0x3dea3d4f,0x3dff3c17,
0x3d153df5,0x3c963dfd,0xbc17bdff,0xbce0bdfa,0x3d8e3dd5,0x3dac3dbe,0xbd9dbdca,0xbdb9bdb1,0x3ded3d44,0x3df83cf9,0xbdf3bd21,0xbdfcbcaf,0x3dfbbcc8,0x3df1bd2c,0xbdf73d09,0xbdea3d4f,
0xbdb53d80,0xbdbe3dac,0xbdb93db1,0xbdc23da7,0xbd153df5,0xbddc3d84,0xbdd83d89,0xbddf3d7c,0xbd713de2,0xbdf13d2c,0xbdef3d38,0xbdf33d21,0xbda23dc6,0xbdfd3c96,0xbdfc3caf,0xbdfe3c7b,
0x3db53d80,0x3ddcbd84,0x3dcabd9d,0x3deabd4f,0xbdff3c49,0x3de73d5b,0x3df33d21,0x3dd83d89,0xbda2bdc6,0x3c963dfd,0x3d093df7,0x3b493e00,0x3d15bdf5,0xbdbe3dac,0xbda73dc2,0xbdd13d93,
0xbdb53d80,0xbdf13d2c,0xbdd83d89,0xbdfe3c7b,0xbd71bde2,0xbc96bdfd,0xbd38bdef,0x3c17bdff,0x3df5bd15,0x3e003bc9,0x3dfcbcaf,0x3df73d09,0x3c493dff,0xbcf93df8,0xbb493e00,0xbd663de5,
0x3db53d80,0x3dfdbc96,0x3de5bd66,0x3dfc3caf,0x3da2bdc6,0xbdbe3dac,0xbd7c3ddf,0xbdea3d4f,0xbc493dff,0x3cf9bdf8,0xbc17bdff,0x3d89bdd8,0xbd71bde2,0x3d2c3df1,0x3d9d3dca,0x3b493e00,
0xbdb53d80,0xbe00bbc9,0xbdef3d38,0xbde5bd66,0x3df53d15,0x3df83cf9,0x3dfcbcaf,0x3dca3d9d,0xbde2bd71,0xbde7bd5b,0xbe00bb49,0xbda7bdc2,0x3dc63da2,0x3dce3d98,0x3dfa3ce0,0x3d7c3ddf,
0x3db53d80,0x3df83cf9,0x3df7bd09,0x3db93db1,0x3c493dff,0xbd2cbdf1,0xbdc2bda7,0x3cafbdfc,0x3dc6bda2,0xbd983dce,0xbc7b3dfe,0xbdea3d4f,0xbdf5bd15,0x3e003bc9,0x3de5bd66,0x3dd83d89,
0xbdb53d80,0xbde7bd5b,0xbdfc3caf,0xbd7cbddf,0xbde23d71,0xbd983dce,0xbb493e00,0xbdf33d21,0x3d153df5,0x3dac3dbe,0x3dfa3ce0,0x3c7b3dfe,0x3dffbc49,0x3ddcbd84,0x3d4fbdea,0x3dff3c17,
0x3db53d80,0x3dce3d98,0x3dffbc17,0x3ce03dfa,0xbdc6bda2,0x3e003bc9,0x3dcabd9d,0x3db93db1,0xbdffbc49,0x3ddcbd84,0x3d21bdf3,0x3dfc3caf,0xbde23d71,0x3d5bbde7,0xbd09bdf7,0x3deabd4f,
0xbdb53d80,0xbdacbdbe,0xbe00bb49,0x3c17bdff,0x3d15bdf5,0xbd84bddc,0xbdfabce0,0x3d09bdf7,0x3d71bde2,0xbd2cbdf1,0xbdeabd4f,0x3d66bde5,0x3da2bdc6,0xbc96bdfd,0xbdd1bd93,0x3d9dbdca,
0x3db53d80,0x3d843ddc,0x3dfe3c7b,0xbd383def,0x3dffbc49,0xbd5b3de7,0x3d663de5,0xbdfa3ce0,0x3da23dc6,0xbdfd3c96,0xbd7c3ddf,0xbdb9bdb1,0xbd153df5,0xbdacbdbe,0xbdff3c17,0x3cafbdfc,
0xbdb53d80,0xbd2cbdf1,0xbdfabce0,0x3d9dbdca,0x3d713de2,0x3dfdbc96,0x3d4fbdea,0x3da73dc2,0xbdf53d15,0xbbc93e00,0x3dd13d93,0xbddf3d7c,0xbc49bdff,0xbdf8bcf9,0xbdb93db1,0xbd21bdf3,
0x3db53d80,0x3c963dfd,0x3df33d21,0xbdd13d93,0xbda23dc6,0xbdacbdbe,0xbdf73d09,0x3d38bdef,0x3c49bdff,0x3df83cf9,0x3da7bdc2,0x3ce03dfa,0x3d713de2,0xbdf13d2c,0xbc7b3dfe,0xbdb9bdb1,
0xbdb53d80,0x3bc9be00,0xbdeabd4f,0x3df3bd21,0xbdf5bd15,0xbcf93df8,0x3dd13d93,0xbdfe3c7b,0x3de23d71,0x3d5bbde7,0xbdb1bdb9,0x3dff3c17,0xbdc6bda2,0xbd983dce,0x3d893dd8,0xbdf7bd09,
0x3db53d80,0xbcf93df8,0x3ddf3d7c,0xbe003b49,0xbc49bdff,0x3df1bd2c,0xbc17bdff,0x3d933dd1,0xbdc63da2,0xbdcebd98,0xbdca3d9d,0x3d38bdef,0x3df53d15,0xbbc93e00,0x3df33d21,0xbdfa3ce0,
0xbdb53d80,0x3d5bbde7,0xbdd1bd93,0x3df73d09,0x3de2bd71,0xbdcebd98,0xbdb93db1,0x3d66bde5,0xbd15bdf5,0xbdbe3dac,0x3d893dd8,0xbdcabd9d,0xbdff3c49,0x3d843ddc,0x3defbd38,0xbdc23da7,
0x3db53d80,0xbd983dce,0x3dc23da7,0xbdd8bd89,0x3dc63da2,0xbbc93e00,0x3dfe3c7b,0xbe003b49,0x3dff3c49,0x3d843ddc,0x3de5bd66,0xbdd13d93,0x3de2bd71,0x3de73d5b,0x3d7cbddf,0xbd383def,
0xbdb53d80,0x3dbebdac,0xbdb1bdb9,0x3da73dc2,0xbd153df5,0x3ddcbd84,0xbd89bdd8,0x3d7c3ddf,0xbd713de2,0x3df1bd2c,0xbd38bdef,0x3d213df3,0xbda23dc6,0x3dfdbc96,0xbcafbdfc,0x3c7b3dfe,
0x3db53d80,0xbddc3d84,0x3d9d3dca,0xbd4fbdea,0xbdff3c49,0xbde7bd5b,0xbd213df3,0x3d89bdd8,0xbda2bdc6,0xbc96bdfd,0xbdf73d09,0x3e00bb49,0x3d15bdf5,0x3dbebdac,0xbdc2bda7,0x3d933dd1,
0xbdb53d80,0x3df1bd2c,0xbd89bdd8,0x3c7b3dfe,0xbd71bde2,0x3c963dfd,0x3defbd38,0xbdffbc17,0x3df5bd15,0xbe00bbc9,0x3caf3dfc,0x3d09bdf7,0x3c493dff,0x3cf9bdf8,0xbe00bb49,0x3de53d66,
0x3db53d80,0xbdfd3c96,0x3d663de5,0x3cafbdfc,0x3da2bdc6,0x3dbebdac,0xbddfbd7c,0x3d4f3dea,0xbc493dff,0xbcf93df8,0x3dffbc17,0xbdd8bd89,0xbd71bde2,0xbd2cbdf1,0xbdca3d9d,0x3e00bb49,
0xbdb53d80,0x3e003bc9,0xbd38bdef,0xbd663de5,0x3df53d15,0xbdf8bcf9,0x3caf3dfc,0x3d9dbdca,0xbde2bd71,0x3de73d5b,0x3b49be00,0xbdc23da7,0x3dc63da2,0xbdcebd98,0xbce03dfa,0x3ddfbd7c,
0x3db53d80,0xbdf8bcf9,0x3d093df7,0x3db1bdb9,0x3c493dff,0x3d2c3df1,0x3da7bdc2,0xbdfcbcaf,0x3dc6bda2,0x3d98bdce,0xbdfebc7b,0x3d4f3dea,0xbdf5bd15,0xbe00bbc9,0x3d663de5,0x3d89bdd8,
0xbdb53d80,0x3de73d5b,0xbcafbdfc,0xbddf3d7c,0xbde23d71,0x3d98bdce,0xbe00bb49,0x3d213df3,0x3d153df5,0xbdacbdbe,0xbce03dfa,0x3dfebc7b,0x3dffbc49,0xbddc3d84,0x3dea3d4f,0x3c17bdff,
0x3db53d80,0xbdcebd98,0x3c173dff,0x3dfabce0,0xbdc6bda2,0xbe00bbc9,0x3d9d3dca,0x3db1bdb9,0xbdffbc49,0xbddc3d84,0x3df33d21,0x3cafbdfc,0xbde23d71,0xbd5b3de7,0x3df7bd09,0xbd4fbdea,
0xbdb53d80,0x3dac3dbe,0x3b49be00,0xbdffbc17,0x3d15bdf5,0x3d843ddc,0x3ce0bdfa,0xbdf7bd09,0x3d71bde2,0x3d2c3df1,0x3d4fbdea,0xbde5bd66,0x3da2bdc6,0x3c963dfd,0x3d93bdd1,0xbdcabd9d,
0x3db53d80,0xbd84bddc,0xbc7b3dfe,0x3def3d38,0x3dffbc49,0x3d5bbde7,0xbde53d66,0x3ce03dfa,0x3da23dc6,0x3dfdbc96,0xbddfbd7c,0xbdb13db9,0xbd153df5,0x3dac3dbe,0xbc17bdff,0xbdfcbcaf,
0xbdb53d80,0x3d2c3df1,0x3ce0bdfa,0xbdcabd9d,0x3d713de2,0xbdfd3c96,0x3dea3d4f,0x3dc2bda7,0xbdf53d15,0x3bc9be00,0xbd933dd1,0x3d7c3ddf,0xbc49bdff,0x3df83cf9,0xbdb1bdb9,0xbdf33d21,
0x3db53d80,0xbc96bdfd,0xbd213df3,0x3d933dd1,0xbda23dc6,0x3dac3dbe,0xbd09bdf7,0xbdefbd38,0x3c49bdff,0xbdf8bcf9,0x3dc23da7,0x3dfabce0,0x3d713de2,0x3df1bd2c,0xbdfebc7b,0xbdb13db9,
0xbdb53d80,0xbbc93e00,0x3d4fbdea,0xbd21bdf3,0xbdf5bd15,0x3cf9bdf8,0xbd933dd1,0x3c7b3dfe,0x3de23d71,0xbd5b3de7,0x3db9bdb1,0x3c17bdff,0xbdc6bda2,0x3d98bdce,0xbdd83d89,0xbd093df7,
0x3db53d80,0x3cf9bdf8,0xbd7c3ddf,0x3b493e00,0xbc49bdff,0xbdf13d2c,0x3dffbc17,0x3dd1bd93,0xbdc63da2,0x3dce3d98,0xbd9dbdca,0xbdefbd38,0x3df53d15,0x3bc9be00,0xbd213df3,0x3ce03dfa,
0xbdb53d80,0xbd5b3de7,0x3d93bdd1,0x3d09bdf7,0x3de2bd71,0x3dce3d98,0xbdb1bdb9,0xbde5bd66,0xbd15bdf5,0x3dbebdac,0xbdd83d89,0xbd9d3dca,0xbdff3c49,0xbd84bddc,0x3d383def,0x3da73dc2,
0x3db53d80,0x3d98bdce,0xbda73dc2,0xbd893dd8,0x3dc63da2,0x3bc9be00,0xbc7b3dfe,0x3b493e00,0x3dff3c49,0xbd84bddc,0x3d663de5,0x3d933dd1,0x3de2bd71,0xbde7bd5b,0x3ddf3d7c,0x3def3d38,
0xbcc83dfb,0xbc493dff,0xbbc93e00,0xbc963dfd,0xbd443ded,0xbd713de2,0xbd5b3de7,0xbd843ddc,0xbdb53db5,0xbdc63da2,0xbdbe3dac,0xbdce3d98,0xbded3d44,0xbdf53d15,0xbdf13d2c,0xbdf83cf9,
0xbd8e3dd5,0xbd153df5,0xbc963dfd,0xbd5b3de7,0xbded3d44,0xbdff3c49,0xbdf83cf9,0xbe00bbc9,0xbdb5bdb5,0xbd71bde2,0xbd98bdce,0xbd2cbdf1,0x3d44bded,0x3da2bdc6,0x3d84bddc,0x3dbebdac,
0xbdd53d8e,0xbd713de2,0xbcf93df8,0xbdac3dbe,0xbdedbd44,0xbda2bdc6,0xbdcebd98,0xbd5bbde7,0x3db5bdb5,0x3df5bd15,0x3ddcbd84,0x3e00bbc9,0x3d443ded,0xbc493dff,0x3c963dfd,0xbd2c3df1,
0xbdfb3cc8,0xbda23dc6,0xbd2c3df1,0xbddc3d84,0xbd44bded,0x3d15bdf5,0xbbc9be00,0x3d98bdce,0x3db53db5,0x3c493dff,0x3d5b3de7,0xbcf93df8,0xbdedbd44,0xbd71bde2,0xbdbebdac,0xbc96bdfd,
0xbdfbbcc8,0xbdc63da2,0xbd5b3de7,0xbdf83cf9,0x3d44bded,0x3df5bd15,0x3dbebdac,0x3dfd3c96,0xbdb53db5,0xbdffbc49,0xbdf13d2c,0xbddcbd84,0x3dedbd44,0x3de23d71,0x3e003bc9,0x3d983dce,
0xbdd5bd8e,0xbde23d71,0xbd843ddc,0xbe00bbc9,0x3dedbd44,0x3dc63da2,0x3dfd3c96,0x3d2c3df1,0xbdb5bdb5,0x3d15bdf5,0xbcf9bdf8,0x3dbebdac,0xbd443ded,0xbdff3c49,0xbdce3d98,0xbde7bd5b,
0xbd8ebdd5,0xbdf53d15,0xbd983dce,0xbdf1bd2c,0x3ded3d44,0xbc493dff,0x3d843ddc,0xbdac3dbe,0x3db5bdb5,0x3de23d71,0x3dfdbc96,0x3d5b3de7,0xbd44bded,0x3dc6bda2,0x3cf9bdf8,0x3e00bbc9,
0xbcc8bdfb,0xbdff3c49,0xbdac3dbe,0xbdcebd98,0x3d443ded,0xbde23d71,0xbd2c3df1,0xbdf8bcf9,0x3db53db5,0xbda23dc6,0x3bc93e00,0xbdfd3c96,0x3ded3d44,0xbd153df5,0x3d5b3de7,0xbddc3d84,
0x3cc8bdfb,0xbdffbc49,0xbdbe3dac,0xbd98bdce,0xbd443ded,0xbde2bd71,0xbdf13d2c,0xbcf9bdf8,0xbdb53db5,0xbda2bdc6,0xbe00bbc9,0x3c96bdfd,0xbded3d44,0xbd15bdf5,0xbde7bd5b,0x3d84bddc,
0x3d8ebdd5,0xbdf5bd15,0xbdce3d98,0xbd2cbdf1,0xbded3d44,0xbc49bdff,0xbddcbd84,0x3dbebdac,0xbdb5bdb5,0x3de2bd71,0x3c96bdfd,0x3de73d5b,0x3d44bded,0x3dc63da2,0x3df8bcf9,0xbbc93e00,
0x3dd5bd8e,0xbde2bd71,0xbddc3d84,0xbbc9be00,0xbdedbd44,0x3dc6bda2,0xbc96bdfd,0x3df13d2c,0x3db5bdb5,0x3d153df5,0x3df83cf9,0xbdac3dbe,0x3d443ded,0xbdffbc49,0xbd983dce,0xbd5bbde7,
0x3dfbbcc8,0xbdc6bda2,0xbde73d5b,0x3cf9bdf8,0xbd44bded,0x3df53d15,0x3dacbdbe,0x3c963dfd,0x3db53db5,0xbdff3c49,0xbd2c3df1,0xbd84bddc,0xbdedbd44,0x3de2bd71,0xbbc9be00,0x3dce3d98,
0x3dfb3cc8,0xbda2bdc6,0xbdf13d2c,0x3d84bddc,0x3d44bded,0x3d153df5,0x3e003bc9,0xbdce3d98,0xbdb53db5,0x3c49bdff,0xbde7bd5b,0x3df8bcf9,0x3dedbd44,0xbd713de2,0x3dac3dbe,0xbdfdbc96,
0x3dd53d8e,0xbd71bde2,0xbdf83cf9,0x3dbebdac,0x3dedbd44,0xbda23dc6,0x3d983dce,0xbde7bd5b,0xbdb5bdb5,0x3df53d15,0x3d84bddc,0xbbc93e00,0xbd443ded,0xbc49bdff,0xbdfdbc96,0x3df1bd2c,
0x3d8e3dd5,0xbd15bdf5,0xbdfd3c96,0x3de7bd5b,0x3ded3d44,0xbdffbc49,0xbcf93df8,0xbbc9be00,0x3db5bdb5,0xbd713de2,0x3dce3d98,0xbdf1bd2c,0xbd44bded,0x3da23dc6,0x3ddcbd84,0xbdac3dbe,
0x3cc83dfb,0xbc49bdff,0xbe003bc9,0x3dfdbc96,0x3d443ded,0xbd71bde2,0xbde73d5b,0x3ddcbd84,0x3db53db5,0xbdc6bda2,0xbdac3dbe,0x3d98bdce,0x3ded3d44,0xbdf5bd15,0xbd2c3df1,0x3cf9bdf8,
0xbcc83dfb,0x3c49bdff,0xbe00bbc9,0x3dfd3c96,0xbd443ded,0x3d71bde2,0xbde7bd5b,0x3ddc3d84,0xbdb53db5,0x3dc6bda2,0xbdacbdbe,0x3d983dce,0xbded3d44,0x3df5bd15,0xbd2cbdf1,0x3cf93df8,
0xbd8e3dd5,0x3d15bdf5,0xbdfdbc96,0x3de73d5b,0xbded3d44,0x3dffbc49,0xbcf9bdf8,0xbbc93e00,0xbdb5bdb5,0x3d713de2,0x3dcebd98,0xbdf13d2c,0x3d44bded,0xbda23dc6,0x3ddc3d84,0xbdacbdbe,
0xbdd53d8e,0x3d71bde2,0xbdf8bcf9,0x3dbe3dac,0xbdedbd44,0x3da23dc6,0x3d98bdce,0xbde73d5b,0x3db5bdb5,0xbdf53d15,0x3d843ddc,0xbbc9be00,0x3d443ded,0x3c49bdff,0xbdfd3c96,0x3df13d2c,
0xbdfb3cc8,0x3da2bdc6,0xbdf1bd2c,0x3d843ddc,0xbd44bded,0xbd153df5,0x3e00bbc9,0xbdcebd98,0x3db53db5,0xbc49bdff,0xbde73d5b,0x3df83cf9,0xbdedbd44,0x3d713de2,0x3dacbdbe,0xbdfd3c96,
0xbdfbbcc8,0x3dc6bda2,0xbde7bd5b,0x3cf93df8,0x3d44bded,0xbdf53d15,0x3dac3dbe,0x3c96bdfd,0xbdb53db5,0x3dff3c49,0xbd2cbdf1,0xbd843ddc,0x3dedbd44,0xbde2bd71,0xbbc93e00,0x3dcebd98,
0xbdd5bd8e,0x3de2bd71,0xbddcbd84,0xbbc93e00,0x3dedbd44,0xbdc6bda2,0xbc963dfd,0x3df1bd2c,0xbdb5bdb5,0xbd153df5,0x3df8bcf9,0xbdacbdbe,0xbd443ded,0x3dffbc49,0xbd98bdce,0xbd5b3de7,
0xbd8ebdd5,0x3df5bd15,0xbdcebd98,0xbd2c3df1,0x3ded3d44,0x3c49bdff,0xbddc3d84,0x3dbe3dac,0x3db5bdb5,0xbde2bd71,0x3c963dfd,0x3de7bd5b,0xbd44bded,0xbdc63da2,0x3df83cf9,0xbbc9be00,
0xbcc8bdfb,0x3dffbc49,0xbdbebdac,0xbd983dce,0x3d443ded,0x3de2bd71,0xbdf1bd2c,0xbcf93df8,0x3db53db5,0x3da2bdc6,0xbe003bc9,0x3c963dfd,0x3ded3d44,0x3d15bdf5,0xbde73d5b,0x3d843ddc,
0x3cc8bdfb,0x3dff3c49,0xbdacbdbe,0xbdce3d98,0xbd443ded,0x3de23d71,0xbd2cbdf1,0xbdf83cf9,0xbdb53db5,0x3da23dc6,0x3bc9be00,0xbdfdbc96,0xbded3d44,0x3d153df5,0x3d5bbde7,0xbddcbd84,
0x3d8ebdd5,0x3df53d15,0xbd98bdce,0xbdf13d2c,0xbded3d44,0x3c493dff,0x3d84bddc,0xbdacbdbe,0xbdb5bdb5,0xbde23d71,0x3dfd3c96,0x3d5bbde7,0x3d44bded,0xbdc6bda2,0x3cf93df8,0x3e003bc9,
0x3dd5bd8e,0x3de23d71,0xbd84bddc,0xbe003bc9,0xbdedbd44,0xbdc63da2,0x3dfdbc96,0x3d2cbdf1,0x3db5bdb5,0xbd15bdf5,0xbcf93df8,0x3dbe3dac,0x3d443ded,0x3dff3c49,0xbdcebd98,0xbde73d5b,
0x3dfbbcc8,0x3dc63da2,0xbd5bbde7,0xbdf8bcf9,0xbd44bded,0xbdf5bd15,0x3dbe3dac,0x3dfdbc96,0x3db53db5,0x3dffbc49,0xbdf1bd2c,0xbddc3d84,0xbdedbd44,0xbde23d71,0x3e00bbc9,0x3d98bdce,
0x3dfb3cc8,0x3da23dc6,0xbd2cbdf1,0xbddcbd84,0x3d44bded,0xbd15bdf5,0xbbc93e00,0x3d983dce,0xbdb53db5,0xbc493dff,0x3d5bbde7,0xbcf9bdf8,0x3dedbd44,0x3d71bde2,0xbdbe3dac,0xbc963dfd,
0x3dd53d8e,0x3d713de2,0xbcf9bdf8,0xbdacbdbe,0x3dedbd44,0x3da2bdc6,0xbdce3d98,0xbd5b3de7,0xbdb5bdb5,0xbdf5bd15,0x3ddc3d84,0x3e003bc9,0xbd443ded,0x3c493dff,0x3c96bdfd,0xbd2cbdf1,
0x3d8e3dd5,0x3d153df5,0xbc96bdfd,0xbd5bbde7,0x3ded3d44,0x3dff3c49,0xbdf8bcf9,0xbe003bc9,0x3db5bdb5,0x3d71bde2,0xbd983dce,0xbd2c3df1,0xbd44bded,0xbda2bdc6,0x3d843ddc,0x3dbe3dac,
0x3cc83dfb,0x3c493dff,0xbbc9be00,0xbc96bdfd,0x3d443ded,0x3d713de2,0xbd5bbde7,0xbd84bddc,0x3db53db5,0x3dc63da2,0xbdbebdac,0xbdcebd98,0x3ded3d44,0x3df53d15,0xbdf1bd2c,0xbdf8bcf9,
0xbd803d80,0xbdffbc49,0xbe00bbc9,0xbdfdbc96,0xbd8e3dd5,0xbde2bd71,0xbde7bd5b,0xbddcbd84,0xbdd53d8e,0xbda2bdc6,0xbdacbdbe,0xbd98bdce,0xbdfb3cc8,0xbd15bdf5,0xbd2cbdf1,0xbcf9bdf8,
0x3d803d80,0x3df53d15,0x3dfd3c96,0x3de73d5b,0xbdfbbcc8,0x3c493dff,0x3cf93df8,0xbbc93e00,0xbcc8bdfb,0xbde23d71,0xbdce3d98,0xbdf13d2c,0x3dd5bd8e,0xbdc6bda2,0xbddcbd84,0xbdacbdbe,
0xbd803d80,0xbde2bd71,0xbdf8bcf9,0xbdbebdac,0xbcc8bdfb,0x3dc6bda2,0x3d98bdce,0x3de7bd5b,0x3dfb3cc8,0x3d153df5,0x3d843ddc,0x3bc93e00,0xbd8e3dd5,0xbdffbc49,0xbdfd3c96,0xbdf1bd2c,
0x3d803d80,0x3dc63da2,0x3df13d2c,0x3d843ddc,0x3dd5bd8e,0xbdf5bd15,0xbe003bc9,0xbdcebd98,0xbd8e3dd5,0x3dffbc49,0x3de7bd5b,0x3df83cf9,0x3cc8bdfb,0xbde23d71,0xbdac3dbe,0xbdfd3c96,
0xbd803d80,0xbda2bdc6,0xbde7bd5b,0xbcf9bdf8,0x3dd53d8e,0x3d153df5,0x3dac3dbe,0xbc963dfd,0xbd8ebdd5,0x3c49bdff,0xbd2cbdf1,0x3d84bddc,0x3cc83dfb,0xbd713de2,0xbbc93e00,0xbdce3d98,
0x3d803d80,0x3d713de2,0x3ddc3d84,0xbbc93e00,0xbcc83dfb,0x3da2bdc6,0x3c96bdfd,0x3df1bd2c,0x3dfbbcc8,0xbdf5bd15,0xbdf83cf9,0xbdacbdbe,0xbd8ebdd5,0x3c493dff,0x3d983dce,0xbd5b3de7,
0xbd803d80,0xbd15bdf5,0xbdcebd98,0x3d2cbdf1,0xbdfb3cc8,0xbdffbc49,0xbddc3d84,0xbdbebdac,0xbcc83dfb,0xbd713de2,0x3c963dfd,0xbde73d5b,0x3dd53d8e,0x3da23dc6,0x3df83cf9,0x3bc93e00,
0x3d803d80,0x3c493dff,0x3dbe3dac,0xbd983dce,0xbd8ebdd5,0x3d713de2,0x3df13d2c,0xbcf93df8,0xbdd5bd8e,0x3dc63da2,0x3e00bbc9,0x3c963dfd,0xbdfbbcc8,0x3df53d15,0x3de7bd5b,0x3d843ddc,
0xbd803d80,0x3c49bdff,0xbdacbdbe,0x3dcebd98,0x3d8ebdd5,0x3d71bde2,0xbd2cbdf1,0x3df8bcf9,0x3dd5bd8e,0x3dc6bda2,0x3bc9be00,0x3dfd3c96,0x3dfbbcc8,0x3df5bd15,0x3d5bbde7,0x3ddc3d84,
0x3d803d80,0xbd153df5,0x3d983dce,0xbdf13d2c,0x3dfb3cc8,0xbdff3c49,0xbd843ddc,0xbdacbdbe,0x3cc83dfb,0xbd71bde2,0xbdfdbc96,0x3d5bbde7,0xbdd53d8e,0x3da2bdc6,0xbcf9bdf8,0x3e003bc9,
0xbd803d80,0x3d71bde2,0xbd84bddc,0x3e00bbc9,0x3cc83dfb,0x3da23dc6,0x3dfdbc96,0xbd2c3df1,0xbdfbbcc8,0xbdf53d15,0xbcf93df8,0xbdbebdac,0x3d8ebdd5,0x3c49bdff,0xbdcebd98,0x3de7bd5b,
0x3d803d80,0xbda23dc6,0x3d5b3de7,0xbdf8bcf9,0xbdd53d8e,0x3d15bdf5,0xbdbebdac,0x3dfdbc96,0x3d8ebdd5,0x3c493dff,0x3df13d2c,0xbddc3d84,0xbcc83dfb,0xbd71bde2,0xbe003bc9,0x3d98bdce,
0xbd803d80,0x3dc6bda2,0xbd2cbdf1,0x3ddc3d84,0xbdd5bd8e,0xbdf53d15,0xbbc93e00,0xbd98bdce,0x3d8e3dd5,0x3dff3c49,0x3d5bbde7,0x3cf93df8,0xbcc8bdfb,0xbde2bd71,0xbdbe3dac,0x3c96bdfd,
0x3d803d80,0xbde23d71,0x3cf93df8,0xbdacbdbe,0x3cc8bdfb,0x3dc63da2,0x3dcebd98,0xbd5b3de7,0xbdfb3cc8,0x3d15bdf5,0xbddcbd84,0x3e003bc9,0x3d8e3dd5,0xbdff3c49,0xbc963dfd,0xbd2cbdf1,
0xbd803d80,0x3df5bd15,0xbc96bdfd,0x3d5b3de7,0x3dfbbcc8,0x3c49bdff,0xbdf8bcf9,0x3e00bbc9,0x3cc8bdfb,0xbde2bd71,0xbd983dce,0x3d2cbdf1,0xbdd5bd8e,0xbdc63da2,0x3d843ddc,0xbdbebdac,
0x3d803d80,0xbdff3c49,0x3bc93e00,0xbc96bdfd,0x3d8e3dd5,0xbde23d71,0x3d5b3de7,0xbd84bddc,0x3dd53d8e,0xbda23dc6,0x3dbe3dac,0xbdcebd98,0x3dfb3cc8,0xbd153df5,0x3df13d2c,0xbdf8bcf9,
0xbd803d80,0x3dff3c49,0x3bc9be00,0xbc963dfd,0xbd8e3dd5,0x3de23d71,0x3d5bbde7,0xbd843ddc,0xbdd53d8e,0x3da23dc6,0x3dbebdac,0xbdce3d98,0xbdfb3cc8,0x3d153df5,0x3df1bd2c,0xbdf83cf9,
0x3d803d80,0xbdf5bd15,0xbc963dfd,0x3d5bbde7,0xbdfbbcc8,0xbc49bdff,0xbdf83cf9,0x3e003bc9,0xbcc8bdfb,0x3de2bd71,0xbd98bdce,0x3d2c3df1,0x3dd5bd8e,0x3dc63da2,0x3d84bddc,0xbdbe3dac,
0xbd803d80,0x3de23d71,0x3cf9bdf8,0xbdac3dbe,0xbcc8bdfb,0xbdc63da2,0x3dce3d98,0xbd5bbde7,0x3dfb3cc8,0xbd15bdf5,0xbddc3d84,0x3e00bbc9,0xbd8e3dd5,0x3dff3c49,0xbc96bdfd,0xbd2c3df1,
0x3d803d80,0xbdc6bda2,0xbd2c3df1,0x3ddcbd84,0x3dd5bd8e,0x3df53d15,0xbbc9be00,0xbd983dce,0xbd8e3dd5,0xbdff3c49,0x3d5b3de7,0x3cf9bdf8,0x3cc8bdfb,0x3de2bd71,0xbdbebdac,0x3c963dfd,
0xbd803d80,0x3da23dc6,0x3d5bbde7,0xbdf83cf9,0x3dd53d8e,0xbd15bdf5,0xbdbe3dac,0x3dfd3c96,0xbd8ebdd5,0xbc493dff,0x3df1bd2c,0xbddcbd84,0x3cc83dfb,0x3d71bde2,0xbe00bbc9,0x3d983dce,
0x3d803d80,0xbd71bde2,0xbd843ddc,0x3e003bc9,0xbcc83dfb,0xbda23dc6,0x3dfd3c96,0xbd2cbdf1,0x3dfbbcc8,0x3df53d15,0xbcf9bdf8,0xbdbe3dac,0xbd8ebdd5,0xbc49bdff,0xbdce3d98,0x3de73d5b,
0xbd803d80,0x3d153df5,0x3d98bdce,0xbdf1bd2c,0xbdfb3cc8,0x3dff3c49,0xbd84bddc,0xbdac3dbe,0xbcc83dfb,0x3d71bde2,0xbdfd3c96,0x3d5b3de7,0x3dd53d8e,0xbda2bdc6,0xbcf93df8,0x3e00bbc9,
0x3d803d80,0xbc49bdff,0xbdac3dbe,0x3dce3d98,0xbd8ebdd5,0xbd71bde2,0xbd2c3df1,0x3df83cf9,0xbdd5bd8e,0xbdc6bda2,0x3bc93e00,0x3dfdbc96,0xbdfbbcc8,0xbdf5bd15,0x3d5b3de7,0x3ddcbd84,
0xbd803d80,0xbc493dff,0x3dbebdac,0xbd98bdce,0x3d8ebdd5,0xbd713de2,0x3df1bd2c,0xbcf9bdf8,0x3dd5bd8e,0xbdc63da2,0x3e003bc9,0x3c96bdfd,0x3dfbbcc8,0xbdf53d15,0x3de73d5b,0x3d84bddc,
0x3d803d80,0x3d15bdf5,0xbdce3d98,0x3d2c3df1,0x3dfb3cc8,0x3dffbc49,0xbddcbd84,0xbdbe3dac,0x3cc83dfb,0x3d713de2,0x3c96bdfd,0xbde7bd5b,0xbdd53d8e,0xbda23dc6,0x3df8bcf9,0x3bc9be00,
0xbd803d80,0xbd713de2,0x3ddcbd84,0xbbc9be00,0x3cc83dfb,0xbda2bdc6,0x3c963dfd,0x3df13d2c,0xbdfbbcc8,0x3df5bd15,0xbdf8bcf9,0xbdac3dbe,0x3d8ebdd5,0xbc493dff,0x3d98bdce,0xbd5bbde7,
0x3d803d80,0x3da2bdc6,0xbde73d5b,0xbcf93df8,0xbdd53d8e,0xbd153df5,0x3dacbdbe,0xbc96bdfd,0x3d8ebdd5,0xbc49bdff,0xbd2c3df1,0x3d843ddc,0xbcc83dfb,0x3d713de2,0xbbc9be00,0xbdcebd98,
0xbd803d80,0xbdc63da2,0x3df1bd2c,0x3d84bddc,0xbdd5bd8e,0x3df5bd15,0xbe00bbc9,0xbdce3d98,0x3d8e3dd5,0xbdffbc49,0x3de73d5b,0x3df8bcf9,0xbcc8bdfb,0x3de23d71,0xbdacbdbe,0xbdfdbc96,
0x3d803d80,0x3de2bd71,0xbdf83cf9,0xbdbe3dac,0x3cc8bdfb,0xbdc6bda2,0x3d983dce,0x3de73d5b,0xbdfb3cc8,0xbd153df5,0x3d84bddc,0x3bc9be00,0x3d8e3dd5,0x3dffbc49,0xbdfdbc96,0xbdf13d2c,
0xbd803d80,0xbdf53d15,0x3dfdbc96,0x3de7bd5b,0x3dfbbcc8,0xbc493dff,0x3cf9bdf8,0xbbc9be00,0x3cc8bdfb,0x3de23d71,0xbdcebd98,0xbdf1bd2c,0xbdd5bd8e,0x3dc6bda2,0xbddc3d84,0xbdac3dbe,
0x3d803d80,0x3dffbc49,0xbe003bc9,0xbdfd3c96,0x3d8e3dd5,0x3de2bd71,0xbde73d5b,0xbddc3d84,0x3dd53d8e,0x3da2bdc6,0xbdac3dbe,0xbd983dce,0x3dfb3cc8,0x3d15bdf5,0xbd2c3df1,0xbcf93df8,
0xbd153df5,0xbc963dfd,0xbc173dff,0xbce03dfa,0xbd8e3dd5,0xbdac3dbe,0xbd9d3dca,0xbdb93db1,0xbded3d44,0xbdf83cf9,0xbdf33d21,0xbdfc3caf,0xbdfbbcc8,0xbdf1bd2c,0xbdf7bd09,0xbdeabd4f,
0xbda23dc6,0xbd2c3df1,0xbcaf3dfc,0xbd7c3ddf,0xbdfb3cc8,0xbdfdbc96,0xbe003b49,0xbdf3bd21,0xbd44bded,0xbbc9be00,0xbce0bdfa,0x3c7bbdfe,0x3dd5bd8e,0x3df8bcf9,0x3deabd4f,0x3dffbc17,
0xbde23d71,0xbd843ddc,0xbd093df7,0xbdb93db1,0xbdd5bd8e,0xbd5bbde7,0xbda7bdc2,0xbcafbdfc,0x3dedbd44,0x3dfd3c96,0x3dfebc7b,0x3dea3d4f,0xbcc83dfb,0xbdac3dbe,0xbd663de5,0xbdd83d89,
0xbdff3c49,0xbdac3dbe,0xbd383def,0xbde53d66,0xbcc8bdfb,0x3d84bddc,0x3cafbdfc,0x3dcabd9d,0x3d443ded,0xbd2c3df1,0x3b493e00,0xbda73dc2,0xbd8ebdd5,0x3c96bdfd,0xbce0bdfa,0x3d7cbddf,
0xbdf5bd15,0xbdce3d98,0xbd663de5,0xbdfc3caf,0x3d8ebdd5,0x3e00bbc9,0x3ddfbd7c,0x3dea3d4f,0xbded3d44,0xbddcbd84,0xbdffbc17,0xbd89bdd8,0x3dfb3cc8,0x3d5b3de7,0x3dca3d9d,0xbb493e00,
0xbdc6bda2,0xbde73d5b,0xbd893dd8,0xbdfebc7b,0x3dfbbcc8,0x3d983dce,0x3def3d38,0x3c173dff,0xbd44bded,0x3dacbdbe,0x3cafbdfc,0x3df7bd09,0xbdd53d8e,0xbddcbd84,0xbe003b49,0xbd66bde5,
0xbd71bde2,0xbdf83cf9,0xbd9d3dca,0xbdeabd4f,0x3dd53d8e,0xbd2c3df1,0x3d213df3,0xbdd83d89,0x3dedbd44,0x3d983dce,0x3df73d09,0xbb493e00,0x3cc8bdfb,0x3e00bbc9,0x3dc2bda7,0x3dd13d93,
0xbc49bdff,0xbe003bc9,0xbdb13db9,0xbdc2bda7,0x3cc83dfb,0xbdf83cf9,0xbd893dd8,0xbddfbd7c,0x3d443ded,0xbde73d5b,0xbd383def,0xbdf3bd21,0x3d8e3dd5,0xbdce3d98,0xbcaf3dfc,0xbdfebc7b,
0x3d15bdf5,0xbdfdbc96,0xbdc23da7,0xbd89bdd8,0xbd8e3dd5,0xbdbebdac,0xbdfe3c7b,0x3b49be00,0xbded3d44,0xbcf9bdf8,0xbde5bd66,0x3d93bdd1,0xbdfbbcc8,0x3d2cbdf1,0xbd7cbddf,0x3defbd38,
0x3da2bdc6,0xbdf1bd2c,0xbdd13d93,0xbd09bdf7,0xbdfb3cc8,0x3c96bdfd,0xbdb9bdb1,0x3de5bd66,0xbd44bded,0x3e00bbc9,0x3d89bdd8,0x3d9d3dca,0x3dd5bd8e,0x3cf93df8,0x3def3d38,0xbda73dc2,
0x3de2bd71,0xbddcbd84,0xbddf3d7c,0x3b49be00,0xbdd5bd8e,0x3de7bd5b,0x3c17bdff,0x3dd13d93,0x3dedbd44,0xbc963dfd,0x3dca3d9d,0xbdef3d38,0xbcc83dfb,0xbdbebdac,0xbdf33d21,0x3ce0bdfa,
0x3dffbc49,0xbdbebdac,0xbdea3d4f,0x3d21bdf3,0xbcc8bdfb,0x3ddc3d84,0x3dd1bd93,0xbc7b3dfe,0x3d443ded,0xbdf1bd2c,0xbdb13db9,0xbc17bdff,0xbd8ebdd5,0x3dfd3c96,0x3d89bdd8,0x3d093df7,
0x3df53d15,0xbd98bdce,0xbdf33d21,0x3d93bdd1,0x3d8ebdd5,0x3bc93e00,0x3df73d09,0xbdef3d38,0xbded3d44,0x3d84bddc,0xbda7bdc2,0x3dfa3ce0,0x3dfb3cc8,0xbde73d5b,0x3c7b3dfe,0xbdb1bdb9,
0x3dc63da2,0xbd5bbde7,0xbdfa3ce0,0x3dcabd9d,0x3dfbbcc8,0xbdce3d98,0x3d4f3dea,0xbdc2bda7,0xbd44bded,0x3dbe3dac,0x3dd1bd93,0xbd7c3ddf,0xbdd53d8e,0x3d84bddc,0xbdb9bdb1,0x3df33d21,
0x3d713de2,0xbcf9bdf8,0xbdfe3c7b,0x3defbd38,0x3dd53d8e,0xbdf1bd2c,0xbd663de5,0x3ce0bdfa,0x3dedbd44,0xbdce3d98,0x3d7c3ddf,0xbdb1bdb9,0x3cc8bdfb,0x3bc93e00,0x3dff3c17,0xbdfc3caf,
0x3c493dff,0xbbc9be00,0xbe003b49,0x3dffbc17,0x3cc83dfb,0xbcf9bdf8,0xbdfa3ce0,0x3df7bd09,0x3d443ded,0xbd5bbde7,0xbdea3d4f,0x3de5bd66,0x3d8e3dd5,0xbd98bdce,0xbdd13d93,0x3dcabd9d,
0xbd153df5,0x3c96bdfd,0xbdffbc17,0x3dfa3ce0,0xbd8e3dd5,0x3dacbdbe,0xbdcabd9d,0x3db13db9,0xbded3d44,0x3df8bcf9,0xbd21bdf3,0x3caf3dfc,0xbdfbbcc8,0x3df13d2c,0x3d09bdf7,0xbd4f3dea,
0xbda23dc6,0x3d2cbdf1,0xbdfcbcaf,0x3ddf3d7c,0xbdfb3cc8,0x3dfd3c96,0xbb49be00,0xbd213df3,0xbd44bded,0x3bc93e00,0x3dfabce0,0xbdfebc7b,0x3dd5bd8e,0xbdf83cf9,0x3d4f3dea,0xbc17bdff,
0xbde23d71,0x3d84bddc,0xbdf7bd09,0x3db13db9,0xbdd5bd8e,0x3d5b3de7,0x3dc2bda7,0xbdfc3caf,0x3dedbd44,0xbdfdbc96,0x3c7b3dfe,0x3d4fbdea,0xbcc83dfb,0x3dacbdbe,0xbde5bd66,0x3d893dd8,
0xbdff3c49,0x3dacbdbe,0xbdefbd38,0x3d663de5,0xbcc8bdfb,0xbd843ddc,0x3dfc3caf,0xbd9dbdca,0x3d443ded,0x3d2cbdf1,0xbe003b49,0x3dc23da7,0xbd8ebdd5,0xbc963dfd,0x3dfabce0,0xbddfbd7c,
0xbdf5bd15,0x3dcebd98,0xbde5bd66,0x3caf3dfc,0x3d8ebdd5,0xbe003bc9,0x3d7c3ddf,0x3d4fbdea,0xbded3d44,0x3ddc3d84,0x3c17bdff,0xbdd83d89,0x3dfb3cc8,0xbd5bbde7,0xbd9d3dca,0x3e003b49,
0xbdc6bda2,0x3de7bd5b,0xbdd8bd89,0xbc7b3dfe,0x3dfbbcc8,0xbd98bdce,0xbd383def,0x3dffbc17,0xbd44bded,0xbdac3dbe,0x3dfc3caf,0xbd09bdf7,0xbdd53d8e,0x3ddc3d84,0xbb49be00,0xbde53d66,
0xbd71bde2,0x3df8bcf9,0xbdcabd9d,0xbd4f3dea,0x3dd53d8e,0x3d2cbdf1,0xbdf33d21,0x3d893dd8,0x3dedbd44,0xbd98bdce,0xbd093df7,0x3e003b49,0x3cc8bdfb,0xbe003bc9,0x3da73dc2,0x3d93bdd1,
0xbc49bdff,0x3e00bbc9,0xbdb9bdb1,0xbda73dc2,0x3cc83dfb,0x3df8bcf9,0xbdd8bd89,0xbd7c3ddf,0x3d443ded,0x3de7bd5b,0xbdefbd38,0xbd213df3,0x3d8e3dd5,0x3dcebd98,0xbdfcbcaf,0xbc7b3dfe,
0x3d15bdf5,0x3dfd3c96,0xbda7bdc2,0xbdd83d89,0xbd8e3dd5,0x3dbe3dac,0xbc7bbdfe,0xbe00bb49,0xbded3d44,0x3cf93df8,0x3d66bde5,0xbdd1bd93,0xbdfbbcc8,0xbd2c3df1,0x3ddfbd7c,0xbd38bdef,
0x3da2bdc6,0x3df13d2c,0xbd93bdd1,0xbdf73d09,0xbdfb3cc8,0xbc963dfd,0x3db1bdb9,0xbd66bde5,0xbd44bded,0xbe003bc9,0x3dd83d89,0x3dcabd9d,0x3dd5bd8e,0xbcf9bdf8,0xbd383def,0x3dc23da7,
0x3de2bd71,0x3ddc3d84,0xbd7cbddf,0xbe00bb49,0xbdd5bd8e,0xbde73d5b,0x3dff3c17,0x3d93bdd1,0x3dedbd44,0x3c96bdfd,0xbd9d3dca,0x3d383def,0xbcc83dfb,0x3dbe3dac,0xbd21bdf3,0xbdfabce0,
0x3dffbc49,0x3dbe3dac,0xbd4fbdea,0xbdf3bd21,0xbcc8bdfb,0xbddcbd84,0x3d933dd1,0x3dfe3c7b,0x3d443ded,0x3df13d2c,0xbdb9bdb1,0xbdff3c17,0xbd8ebdd5,0xbdfdbc96,0x3dd83d89,0x3df7bd09,
0x3df53d15,0x3d983dce,0xbd21bdf3,0xbdd1bd93,0x3d8ebdd5,0xbbc9be00,0xbd093df7,0x3d383def,0xbded3d44,0xbd843ddc,0x3dc2bda7,0x3ce0bdfa,0x3dfb3cc8,0x3de7bd5b,0xbdfe3c7b,0xbdb93db1,
0x3dc63da2,0x3d5b3de7,0xbce0bdfa,0xbd9dbdca,0x3dfbbcc8,0x3dcebd98,0xbdea3d4f,0xbda73dc2,0xbd44bded,0xbdbebdac,0x3d933dd1,0x3ddf3d7c,0xbdd53d8e,0xbd843ddc,0x3db1bdb9,0x3d21bdf3,
0x3d713de2,0x3cf93df8,0xbc7bbdfe,0xbd38bdef,0x3dd53d8e,0x3df13d2c,0xbde5bd66,0xbdfabce0,0x3dedbd44,0x3dcebd98,0xbddf3d7c,0xbdb93db1,0x3cc8bdfb,0xbbc9be00,0xbc173dff,0x3caf3dfc,
0x3c493dff,0x3bc93e00,0xbb49be00,0xbc17bdff,0x3cc83dfb,0x3cf93df8,0xbce0bdfa,0xbd09bdf7,0x3d443ded,0x3d5b3de7,0xbd4fbdea,0xbd66bde5,0x3d8e3dd5,0x3d983dce,0xbd93bdd1,0xbd9dbdca,
0xbdb53d80,0xbd98bdce,0xbda7bdc2,0xbd89bdd8,0xbdc63da2,0xbbc9be00,0xbc7bbdfe,0x3b49be00,0xbdff3c49,0x3d84bddc,0x3d66bde5,0x3d93bdd1,0xbde2bd71,0x3de7bd5b,0x3ddfbd7c,0x3defbd38,
0x3db53d80,0x3d5b3de7,0x3d933dd1,0x3d093df7,0xbde2bd71,0xbdce3d98,0xbdb13db9,0xbde53d66,0x3d15bdf5,0xbdbebdac,0xbdd8bd89,0xbd9dbdca,0x3dff3c49,0x3d84bddc,0x3d38bdef,0x3da7bdc2,
0xbdb53d80,0xbcf9bdf8,0xbd7cbddf,0x3b49be00,0x3c49bdff,0x3df13d2c,0x3dff3c17,0x3dd13d93,0x3dc63da2,0xbdce3d98,0xbd9d3dca,0xbdef3d38,0xbdf53d15,0xbbc9be00,0xbd21bdf3,0x3ce0bdfa,
0x3db53d80,0x3bc93e00,0x3d4f3dea,0xbd213df3,0x3df5bd15,0xbcf9bdf8,0xbd93bdd1,0x3c7bbdfe,0xbde23d71,0x3d5b3de7,0x3db93db1,0x3c173dff,0x3dc6bda2,0xbd98bdce,0xbdd8bd89,0xbd09bdf7,
0xbdb53d80,0x3c96bdfd,0xbd21bdf3,0x3d93bdd1,0x3da23dc6,0xbdac3dbe,0xbd093df7,0xbdef3d38,0xbc49bdff,0x3df8bcf9,0x3dc2bda7,0x3dfa3ce0,0xbd713de2,0xbdf1bd2c,0xbdfe3c7b,0xbdb1bdb9,
0x3db53d80,0xbd2c3df1,0x3ce03dfa,0xbdca3d9d,0xbd713de2,0x3dfd3c96,0x3deabd4f,0x3dc23da7,0x3df53d15,0xbbc9be00,0xbd93bdd1,0x3d7cbddf,0x3c49bdff,0xbdf83cf9,0xbdb13db9,0xbdf3bd21,
0xbdb53d80,0x3d84bddc,0xbc7bbdfe,0x3defbd38,0xbdffbc49,0xbd5bbde7,0xbde5bd66,0x3ce0bdfa,0xbda23dc6,0xbdfdbc96,0xbddf3d7c,0xbdb1bdb9,0x3d153df5,0xbdac3dbe,0xbc173dff,0xbdfc3caf,
0x3db53d80,0xbdac3dbe,0x3b493e00,0xbdff3c17,0xbd15bdf5,0xbd843ddc,0x3ce03dfa,0xbdf73d09,0xbd71bde2,0xbd2c3df1,0x3d4f3dea,0xbde53d66,0xbda2bdc6,0xbc963dfd,0x3d933dd1,0xbdca3d9d,
0xbdb53d80,0x3dcebd98,0x3c17bdff,0x3dfa3ce0,0x3dc6bda2,0x3e00bbc9,0x3d9dbdca,0x3db13db9,0x3dffbc49,0x3ddc3d84,0x3df3bd21,0x3caf3dfc,0x3de23d71,0x3d5b3de7,0x3df73d09,0xbd4f3dea,
0x3db53d80,0xbde73d5b,0xbcaf3dfc,0xbddfbd7c,0x3de23d71,0xbd98bdce,0xbe003b49,0x3d21bdf3,0xbd153df5,0x3dacbdbe,0xbce0bdfa,0x3dfe3c7b,0xbdffbc49,0x3ddc3d84,0x3deabd4f,0x3c173dff,
0xbdb53d80,0x3df8bcf9,0x3d09bdf7,0x3db13db9,0xbc493dff,0xbd2c3df1,0x3da73dc2,0xbdfc3caf,0xbdc6bda2,0xbd98bdce,0xbdfe3c7b,0x3d4fbdea,0x3df5bd15,0x3e00bbc9,0x3d66bde5,0x3d893dd8,
0x3db53d80,0xbe003bc9,0xbd383def,0xbd66bde5,0xbdf53d15,0x3df8bcf9,0x3cafbdfc,0x3d9d3dca,0x3de2bd71,0xbde73d5b,0x3b493e00,0xbdc2bda7,0xbdc63da2,0x3dcebd98,0xbce0bdfa,0x3ddf3d7c,
0xbdb53d80,0x3dfd3c96,0x3d66bde5,0x3caf3dfc,0xbda2bdc6,0xbdbebdac,0xbddf3d7c,0x3d4fbdea,0x3c493dff,0x3cf93df8,0x3dff3c17,0xbdd83d89,0x3d71bde2,0x3d2cbdf1,0xbdcabd9d,0x3e003b49,
0x3db53d80,0xbdf1bd2c,0xbd893dd8,0x3c7bbdfe,0x3d71bde2,0xbc963dfd,0x3def3d38,0xbdff3c17,0xbdf5bd15,0x3e00bbc9,0x3cafbdfc,0x3d093df7,0xbc493dff,0xbcf9bdf8,0xbe003b49,0x3de5bd66,
0xbdb53d80,0x3ddc3d84,0x3d9dbdca,0xbd4f3dea,0x3dff3c49,0x3de7bd5b,0xbd21bdf3,0x3d893dd8,0x3da2bdc6,0x3c96bdfd,0xbdf7bd09,0x3e003b49,0xbd15bdf5,0xbdbebdac,0xbdc23da7,0x3d93bdd1,
0x3db53d80,0xbdbebdac,0xbdb13db9,0x3da7bdc2,0x3d153df5,0xbddcbd84,0xbd893dd8,0x3d7cbddf,0x3d713de2,0xbdf1bd2c,0xbd383def,0x3d21bdf3,0x3da23dc6,0xbdfdbc96,0xbcaf3dfc,0x3c7bbdfe,
0xbdb53d80,0x3d983dce,0x3dc2bda7,0xbdd83d89,0xbdc63da2,0x3bc93e00,0x3dfebc7b,0xbe00bb49,0xbdff3c49,0xbd843ddc,0x3de53d66,0xbdd1bd93,0xbde2bd71,0xbde73d5b,0x3d7c3ddf,0xbd38bdef,
0x3db53d80,0xbd5bbde7,0xbdd13d93,0x3df7bd09,0xbde2bd71,0x3dcebd98,0xbdb9bdb1,0x3d663de5,0x3d15bdf5,0x3dbe3dac,0x3d89bdd8,0xbdca3d9d,0x3dff3c49,0xbd843ddc,0x3def3d38,0xbdc2bda7,
0xbdb53d80,0x3cf93df8,0x3ddfbd7c,0xbe00bb49,0x3c49bdff,0xbdf1bd2c,0xbc173dff,0x3d93bdd1,0x3dc63da2,0x3dcebd98,0xbdcabd9d,0x3d383def,0xbdf53d15,0x3bc93e00,0x3df3bd21,0xbdfabce0,
0x3db53d80,0xbbc9be00,0xbdea3d4f,0x3df33d21,0x3df5bd15,0x3cf93df8,0x3dd1bd93,0xbdfebc7b,0xbde23d71,0xbd5bbde7,0xbdb13db9,0x3dffbc17,0x3dc6bda2,0x3d983dce,0x3d89bdd8,0xbdf73d09,
0xbdb53d80,0xbc963dfd,0x3df3bd21,0xbdd1bd93,0x3da23dc6,0x3dacbdbe,0xbdf7bd09,0x3d383def,0xbc49bdff,0xbdf83cf9,0x3da73dc2,0x3ce0bdfa,0xbd713de2,0x3df13d2c,0xbc7bbdfe,0xbdb93db1,
0x3db53d80,0x3d2cbdf1,0xbdfa3ce0,0x3d9d3dca,0xbd713de2,0xbdfdbc96,0x3d4f3dea,0x3da7bdc2,0x3df53d15,0x3bc93e00,0x3dd1bd93,0xbddfbd7c,0x3c49bdff,0x3df8bcf9,0xbdb9bdb1,0xbd213df3,
0xbdb53d80,0xbd843ddc,0x3dfebc7b,0xbd38bdef,0xbdffbc49,0x3d5b3de7,0x3d66bde5,0xbdfabce0,0xbda23dc6,0x3dfd3c96,0xbd7cbddf,0xbdb93db1,0x3d153df5,0x3dacbdbe,0xbdffbc17,0x3caf3dfc,
0x3db53d80,0x3dacbdbe,0xbe003b49,0x3c173dff,0xbd15bdf5,0x3d84bddc,0xbdfa3ce0,0x3d093df7,0xbd71bde2,0x3d2cbdf1,0xbdea3d4f,0x3d663de5,0xbda2bdc6,0x3c96bdfd,0xbdd13d93,0x3d9d3dca,
0xbdb53d80,0xbdce3d98,0x3dff3c17,0x3ce0bdfa,0x3dc6bda2,0xbe003bc9,0x3dca3d9d,0x3db9bdb1,0x3dffbc49,0xbddcbd84,0x3d213df3,0x3dfcbcaf,0x3de23d71,0xbd5bbde7,0xbd093df7,0x3dea3d4f,
0x3db53d80,0x3de7bd5b,0xbdfcbcaf,0xbd7c3ddf,0x3de23d71,0x3d983dce,0xbb49be00,0xbdf3bd21,0xbd153df5,0xbdac3dbe,0x3dfabce0,0x3c7bbdfe,0xbdffbc49,0xbddcbd84,0x3d4f3dea,0x3dffbc17,
0xbdb53d80,0xbdf83cf9,0x3df73d09,0x3db9bdb1,0xbc493dff,0x3d2cbdf1,0xbdc23da7,0x3caf3dfc,0xbdc6bda2,0x3d983dce,0xbc7bbdfe,0xbdeabd4f,0x3df5bd15,0xbe003bc9,0x3de53d66,0x3dd8bd89,
0x3db53d80,0x3e00bbc9,0xbdefbd38,0xbde53d66,0xbdf53d15,0xbdf83cf9,0x3dfc3caf,0x3dcabd9d,0x3de2bd71,0x3de7bd5b,0xbe003b49,0xbda73dc2,0xbdc63da2,0xbdce3d98,0x3dfabce0,0x3d7cbddf,
0xbdb53d80,0xbdfdbc96,0x3de53d66,0x3dfcbcaf,0xbda2bdc6,0x3dbe3dac,0xbd7cbddf,0xbdeabd4f,0x3c493dff,0xbcf9bdf8,0xbc173dff,0x3d893dd8,0x3d71bde2,0xbd2c3df1,0x3d9dbdca,0x3b49be00,
0x3db53d80,0x3df13d2c,0xbdd8bd89,0xbdfebc7b,0x3d71bde2,0x3c96bdfd,0xbd383def,0x3c173dff,0xbdf5bd15,0xbe003bc9,0x3dfc3caf,0x3df7bd09,0xbc493dff,0x3cf93df8,0xbb49be00,0xbd66bde5,
0xbdb53d80,0xbddcbd84,0x3dca3d9d,0x3dea3d4f,0x3dff3c49,0xbde73d5b,0x3df3bd21,0x3dd8bd89,0x3da2bdc6,0xbc963dfd,0x3d09bdf7,0x3b49be00,0xbd15bdf5,0x3dbe3dac,0xbda7bdc2,0xbdd1bd93,
0x3db53d80,0x3dbe3dac,0xbdb9bdb1,0xbdc2bda7,0x3d153df5,0x3ddc3d84,0xbdd8bd89,0xbddfbd7c,0x3d713de2,0x3df13d2c,0xbdefbd38,0xbdf3bd21,0x3da23dc6,0x3dfd3c96,0xbdfcbcaf,0xbdfebc7b,
0x3f800000,0x0,0x3f800000,0x0,0x3f800000,0x0,0x3f800000,0x0,0x3f800000,0x0,0x3f800000,0x0,0x3f800000,0x0,0x3f800000,0x0,
0x3f800000,0x0,0x3f7ffb11,0xbc490e90,0x3f7fec43,0xbcc90ab0,0x3f7fd397,0xbd16c32c,0x3f7fb10f,0xbd48fb30,0x3f7f84ab,0xbd7b2b74,0x3f7f4e6d,0xbd96a905,0x3f7f0e58,0xbdafb680,
0x3f800000,0x0,0x3f7fec43,0xbcc90ab0,0x3f7fb10f,0xbd48fb30,0x3f7f4e6d,0xbd96a905,0x3f7ec46d,0xbdc8bd36,0x3f7e1324,0xbdfab273,0x3f7d3aac,0xbe164083,0x3f7c3b28,0xbe2f10a2,
0x3f800000,0x0,0x3f7fd397,0xbd16c32c,0x3f7f4e6d,0xbd96a905,0x3f7e70b0,0xbde1bc2e,0x3f7d3aac,0xbe164083,0x3f7baccd,0xbe3b6ecf,0x3f79c79d,0xbe605c13,0x3f778bc5,0xbe827dc0,
0x3f800000,0x0,0x3f7fb10f,0xbd48fb30,0x3f7ec46d,0xbdc8bd36,0x3f7d3aac,0xbe164083,0x3f7b14be,0xbe47c5c2,0x3f7853f8,0xbe78cfcc,0x3f74fa0b,0xbe94a031,0x3f710908,0xbeac7cd4,
0x3f800000,0x0,0x3f7f84ab,0xbd7b2b74,0x3f7e1324,0xbdfab273,0x3f7baccd,0xbe3b6ecf,0x3f7853f8,0xbe78cfcc,0x3f740bdd,0xbe9aa086,0x3f6ed89e,0xbeb8442a,0x3f68bf3c,0xbed53641,
0x3f800000,0x0,0x3f7f4e6d,0xbd96a905,0x3f7d3aac,0xbe164083,0x3f79c79d,0xbe605c13,0x3f74fa0b,0xbe94a031,0x3f6ed89e,0xbeb8442a,0x3f676bd8,0xbedae880,0x3f5ebe05,0xbefc5d27,
0x3f800000,0x0,0x3f7f0e58,0xbdafb680,0x3f7c3b28,0xbe2f10a2,0x3f778bc5,0xbe827dc0,0x3f710908,0xbeac7cd4,0x3f68bf3c,0xbed53641,0x3f5ebe05,0xbefc5d27,0x3f531849,0xbf10d3cd,
0x3f800000,0x0,0x3f7b14be,0xbe47c5c2,0x3f6c835e,0xbec3ef15,0x3f54db31,0xbf0e39da,0x3f3504f3,0xbf3504f3,0x3f0e39da,0xbf54db31,0x3ec3ef15,0xbf6c835e,0x3e47c5c2,0xbf7b14be,
0x3f800000,0x0,0x3f7a7302,0xbe541501,0x3f6a09a7,0xbecf7bca,0x3f4f7a1f,0xbf15f6d9,0x3f2beb4a,0xbf3daef9,0x3f00e7e4,0xbf5d2d53,0x3ea09ae5,0xbf731447,0x3de1bc2e,0xbf7e70b0,
0x3f800000,0x0,0x3f79c79d,0xbe605c13,0x3f676bd8,0xbedae880,0x3f49d112,0xbf1d7fd1,0x3f226799,0xbf45e403,0x3ee63375,0xbf64aa59,0x3e78cfcc,0xbf7853f8,0x3cc90ab0,0xbf7fec43,
0x3f800000,0x0,0x3f791298,0xbe6c9a7f,0x3f64aa59,0xbee63375,0x3f43e200,0xbf24d225,0x3f187fc0,0xbf4d9f02,0x3ec9b953,0xbf6b4b0c,0x3e2f10a2,0xbf7c3b28,0xbd7b2b74,0xbf7f84ab,
0x3f800000,0x0,0x3f7853f8,0xbe78cfcc,0x3f61c598,0xbef15aea,0x3f3daef9,0xbf2beb4a,0x3f0e39da,0xbf54db31,0x3eac7cd4,0xbf710908,0x3dc8bd36,0xbf7ec46d,0xbe164083,0xbf7d3aac,
0x3f800000,0x0,0x3f778bc5,0xbe827dc0,0x3f5ebe05,0xbefc5d27,0x3f373a23,0xbf32c8c9,0x3f039c3d,0xbf5b941a,0x3e8e9a22,0xbf75dec6,0x3cc90ab0,0xbf7fec43,0xbe6c9a7f,0xbf791298,
0x3f800000,0x0,0x3f76ba07,0xbe888e93,0x3f5b941a,0xbf039c3d,0x3f3085bb,0xbf396842,0x3ef15aea,0xbf61c598,0x3e605c13,0xbf79c79d,0xbd48fb30,0xbf7fb10f,0xbea09ae5,0xbf731447,
0x3f800000,0x0,0x3f75dec6,0xbe8e9a22,0x3f584853,0xbf08f59b,0x3f299415,0xbf3fc767,0x3edae880,0xbf676bd8,0x3e22abb6,0xbf7cbfc9,0xbdfab273,0xbf7e1324,0xbec9b953,0xbf6b4b0c,
0x3f800000,0x0,0x3f7ec46d,0xbdc8bd36,0x3f7b14be,0xbe47c5c2,0x3f74fa0b,0xbe94a031,0x3f6c835e,0xbec3ef15,0x3f61c598,0xbef15aea,0x3f54db31,0xbf0e39da,0x3f45e403,0xbf226799,
0x3f800000,0x0,0x3f6b4b0c,0xbec9b953,0x3f3085bb,0xbf396842,0x3eb263ef,0xbf6ff573,0xbd48fb30,0xbf7fb10f,0xbee0924f,0xbf660f88,0xbf41d870,0xbf273656,0xbf740bdd,0xbe9aa086,
0x3f800000,0x0,0x3f6a09a7,0xbecf7bca,0x3f2beb4a,0xbf3daef9,0x3ea09ae5,0xbf731447,0xbdc8bd36,0xbf7ec46d,0xbefc5d27,0xbf5ebe05,0xbf4d9f02,0xbf187fc0,0xbf79c79d,0xbe605c13,
0x3f800000,0x0,0x3f68bf3c,0xbed53641,0x3f273656,0xbf41d870,0x3e8e9a22,0xbf75dec6,0xbe164083,0xbf7d3aac,0xbf0b9a6b,0xbf5695e5,0xbf584853,0xbf08f59b,0xbf7dabcc,0xbe09cf86,
0x3f800000,0x0,0x3f676bd8,0xbedae880,0x3f226799,0xbf45e403,0x3e78cfcc,0xbf7853f8,0xbe47c5c2,0xbf7b14be,0xbf187fc0,0xbf4d9f02,0xbf61c598,0xbef15aea,0xbf7fb10f,0xbd48fb30,
0x3f800000,0x0,0x3f660f88,0xbee0924f,0x3f1d7fd1,0xbf49d112,0x3e541501,0xbf7a7302,0xbe78cfcc,0xbf7853f8,0xbf24d225,0xbf43e200,0xbf6a09a7,0xbecf7bca,0xbf7fd397,0x3d16c32c,
0x3f800000,0x0,0x3f64aa59,0xbee63375,0x3f187fc0,0xbf4d9f02,0x3e2f10a2,0xbf7c3b28,0xbe94a031,0xbf74fa0b,0xbf3085bb,0xbf396842,0xbf710908,0xbeac7cd4,0xbf7e1324,0x3dfab273,
0x3f800000,0x0,0x3f633c5a,0xbeebcbbb,0x3f13682a,0xbf514d3d,0x3e09cf86,0xbf7dabcc,0xbeac7cd4,0xbf710908,0xbf3b8f3b,0xbf2e3bde,0xbf76ba07,0xbe888e93,0xbf7a7302,0x3e541501,
0x3f800000,0x0,0x3f74fa0b,0xbe94a031,0x3f54db31,0xbf0e39da,0x3f226799,0xbf45e403,0x3ec3ef15,0xbf6c835e,0x3dc8bd36,0xbf7ec46d,0xbe47c5c2,0xbf7b14be,0xbef15aea,0xbf61c598,
0x3f800000,0x0,0x3f531849,0xbf10d3cd,0x3eb8442a,0xbf6ed89e,0xbe6c9a7f,0xbf791298,0xbf3daef9,0xbf2beb4a,0xbf7dabcc,0xbe09cf86,0xbf64aa59,0x3ee63375,0xbef6e0cb,0x3f604621,
0x3f800000,0x0,0x3f514d3d,0xbf13682a,0x3eac7cd4,0xbf710908,0xbe888e93,0xbf76ba07,0xbf45e403,0xbf226799,0xbf7f4e6d,0xbd96a905,0xbf5b941a,0x3f039c3d,0xbecf7bca,0x3f6a09a7,
0x3f800000,0x0,0x3f4f7a1f,0xbf15f6d9,0x3ea09ae5,0xbf731447,0xbe9aa086,0xbf740bdd,0xbf4d9f02,0xbf187fc0,0xbf7ffb11,0xbc490e90,0xbf514d3d,0x3f13682a,0xbea68f12,0x3f721352,
0x3f800000,0x0,0x3f4d9f02,0xbf187fc0,0x3e94a031,0xbf74fa0b,0xbeac7cd4,0xbf710908,0xbf54db31,0xbf0e39da,0xbf7fb10f,0x3d48fb30,0xbf45e403,0x3f226799,0xbe78cfcc,0x3f7853f8,
0x3f800000,0x0,0x3f4bbbf8,0xbf1b02c6,0x3e888e93,0xbf76ba07,0xbebe1d4a,0xbf6db293,0xbf5b941a,0xbf039c3d,0xbf7e70b0,0x3de1bc2e,0xbf396842,0x3f3085bb,0xbe22abb6,0x3f7cbfc9,
0x3f800000,0x0,0x3f49d112,0xbf1d7fd1,0x3e78cfcc,0xbf7853f8,0xbecf7bca,0xbf6a09a7,0xbf61c598,0xbef15aea,0xbf7c3b28,0x3e2f10a2,0xbf2beb4a,0x3f3daef9,0xbd96a905,0x3f7f4e6d,
0x3f800000,0x0,0x3f47de65,0xbf1ff6cb,0x3e605c13,0xbf79c79d,0xbee0924f,0xbf660f88,0xbf676bd8,0xbedae880,0xbf791298,0x3e6c9a7f,0xbf1d7fd1,0x3f49d112,0x3c490e90,0x3f7ffb11,
0x3f800000,0x0,0x3f800000,0x0,0x3f800000,0x0,0x3f800000,0x0,0x40000000,0x0,0x3f800000,0x0,0x3f800000,0x0,0x3f800000,0x0,
0x3f800000,0x0,0x3f7ffb11,0xbc490e90,0x3f7fec43,0xbcc90ab0,0x3f7fd397,0xbd16c32c,0x3fffb10f,0xbdc8fb30,0x3f7f84ab,0xbd7b2b74,0x3f7f4e6d,0xbd96a905,0x3f7f0e58,0xbdafb680,
0x3f800000,0x0,0x3f7fec43,0xbcc90ab0,0x3f7fb10f,0xbd48fb30,0x3f7f4e6d,0xbd96a905,0x3ffec46d,0xbe48bd36,0x3f7e1324,0xbdfab273,0x3f7d3aac,0xbe164083,0x3f7c3b28,0xbe2f10a2,
0x3f800000,0x0,0x3f7fd397,0xbd16c32c,0x3f7f4e6d,0xbd96a905,0x3f7e70b0,0xbde1bc2e,0x3ffd3aac,0xbe964083,0x3f7baccd,0xbe3b6ecf,0x3f79c79d,0xbe605c13,0x3f778bc5,0xbe827dc0,
0x3f800000,0x0,0x3f7fb10f,0xbd48fb30,0x3f7ec46d,0xbdc8bd36,0x3f7d3aac,0xbe164083,0x3ffb14be,0xbec7c5c2,0x3f7853f8,0xbe78cfcc,0x3f74fa0b,0xbe94a031,0x3f710908,0xbeac7cd4,
0x3f800000,0x0,0x3f7f84ab,0xbd7b2b74,0x3f7e1324,0xbdfab273,0x3f7baccd,0xbe3b6ecf,0x3ff853f8,0xbef8cfcc,0x3f740bdd,0xbe9aa086,0x3f6ed89e,0xbeb8442a,0x3f68bf3c,0xbed53641,
0x3f800000,0x0,0x3f7f4e6d,0xbd96a905,0x3f7d3aac,0xbe164083,0x3f79c79d,0xbe605c13,0x3ff4fa0b,0xbf14a031,0x3f6ed89e,0xbeb8442a,0x3f676bd8,0xbedae880,0x3f5ebe05,0xbefc5d27,
0x3f800000,0x0,0x3f7f0e58,0xbdafb680,0x3f7c3b28,0xbe2f10a2,0x3f778bc5,0xbe827dc0,0x3ff10908,0xbf2c7cd4,0x3f68bf3c,0xbed53641,0x3f5ebe05,0xbefc5d27,0x3f531849,0xbf10d3cd,
0x3f800000,0x0,0x3f7ec46d,0xbdc8bd36,0x3f7b14be,0xbe47c5c2,0x3f74fa0b,0xbe94a031,0x3fec835e,0xbf43ef15,0x3f61c598,0xbef15aea,0x3f54db31,0xbf0e39da,0x3f45e403,0xbf226799,
0x3f800000,0x0,0x3f7e70b0,0xbde1bc2e,0x3f79c79d,0xbe605c13,0x3f721352,0xbea68f12,0x3fe76bd8,0xbf5ae880,0x3f59f26a,0xbf064b82,0x3f49d112,0xbf1d7fd1,0x3f373a23,0xbf32c8c9,
0x3f800000,0x0,0x3f7e1324,0xbdfab273,0x3f7853f8,0xbe78cfcc,0x3f6ed89e,0xbeb8442a,0x3fe1c598,0xbf715aea,0x3f514d3d,0xbf13682a,0x3f3daef9,0xbf2beb4a,0x3f273656,0xbf41d870,
0x3f800000,0x0,0x3f7dabcc,0xbe09cf86,0x3f76ba07,0xbe888e93,0x3f6b4b0c,0xbec9b953,0x3fdb941a,0xbf839c3d,0x3f47de65,0xbf1ff6cb,0x3f3085bb,0xbf396842,0x3f15f6d9,0xbf4f7a1f,
0x3f800000,0x0,0x3f7d3aac,0xbe164083,0x3f74fa0b,0xbe94a031,0x3f676bd8,0xbedae880,0x3fd4db31,0xbf8e39da,0x3f3daef9,0xbf2beb4a,0x3f226799,0xbf45e403,0x3f039c3d,0xbf5b941a,
0x3f800000,0x0,0x3f7cbfc9,0xbe22abb6,0x3f731447,0xbea09ae5,0x3f633c5a,0xbeebcbbb,0x3fcd9f02,0xbf987fc0,0x3f32c8c9,0xbf373a23,0x3f13682a,0xbf514d3d,0x3ee0924f,0xbf660f88,
0x3f800000,0x0,0x3f7c3b28,0xbe2f10a2,0x3f710908,0xbeac7cd4,0x3f5ebe05,0xbefc5d27,0x3fc5e403,0xbfa26799,0x3f273656,0xbf41d870,0x3f039c3d,0xbf5b941a,0x3eb8442a,0xbf6ed89e,
0x3f800000,0x0,0x3f7baccd,0xbe3b6ecf,0x3f6ed89e,0xbeb8442a,0x3f59f26a,0xbf064b82,0x3fbdaef9,0xbfabeb4a,0x3f1b02c6,0xbf4bbbf8,0x3ee63375,0xbf64aa59,0x3e8e9a22,0xbf75dec6,
0x3f800000,0x0,0x3f7b14be,0xbe47c5c2,0x3f6c835e,0xbec3ef15,0x3f54db31,0xbf0e39da,0x3fb504f3,0xbfb504f3,0x3f0e39da,0xbf54db31,0x3ec3ef15,0xbf6c835e,0x3e47c5c2,0xbf7b14be,
0x3f800000,0x0,0x3f7a7302,0xbe541501,0x3f6a09a7,0xbecf7bca,0x3f4f7a1f,0xbf15f6d9,0x3fabeb4a,0xbfbdaef9,0x3f00e7e4,0xbf5d2d53,0x3ea09ae5,0xbf731447,0x3de1bc2e,0xbf7e70b0,
0x3f800000,0x0,0x3f79c79d,0xbe605c13,0x3f676bd8,0xbedae880,0x3f49d112,0xbf1d7fd1,0x3fa26799,0xbfc5e403,0x3ee63375,0xbf64aa59,0x3e78cfcc,0xbf7853f8,0x3cc90ab0,0xbf7fec43,
0x3f800000,0x0,0x3f791298,0xbe6c9a7f,0x3f64aa59,0xbee63375,0x3f43e200,0xbf24d225,0x3f987fc0,0xbfcd9f02,0x3ec9b953,0xbf6b4b0c,0x3e2f10a2,0xbf7c3b28,0xbd7b2b74,0xbf7f84ab,
0x3f800000,0x0,0x3f7853f8,0xbe78cfcc,0x3f61c598,0xbef15aea,0x3f3daef9,0xbf2beb4a,0x3f8e39da,0xbfd4db31,0x3eac7cd4,0xbf710908,0x3dc8bd36,0xbf7ec46d,0xbe164083,0xbf7d3aac,
0x3f800000,0x0,0x3f778bc5,0xbe827dc0,0x3f5ebe05,0xbefc5d27,0x3f373a23,0xbf32c8c9,0x3f839c3d,0xbfdb941a,0x3e8e9a22,0xbf75dec6,0x3cc90ab0,0xbf7fec43,0xbe6c9a7f,0xbf791298,
0x3f800000,0x0,0x3f76ba07,0xbe888e93,0x3f5b941a,0xbf039c3d,0x3f3085bb,0xbf396842,0x3f715aea,0xbfe1c598,0x3e605c13,0xbf79c79d,0xbd48fb30,0xbf7fb10f,0xbea09ae5,0xbf731447,
0x3f800000,0x0,0x3f75dec6,0xbe8e9a22,0x3f584853,0xbf08f59b,0x3f299415,0xbf3fc767,0x3f5ae880,0xbfe76bd8,0x3e22abb6,0xbf7cbfc9,0xbdfab273,0xbf7e1324,0xbec9b953,0xbf6b4b0c,
0x3f800000,0x0,0x3f74fa0b,0xbe94a031,0x3f54db31,0xbf0e39da,0x3f226799,0xbf45e403,0x3f43ef15,0xbfec835e,0x3dc8bd36,0xbf7ec46d,0xbe47c5c2,0xbf7b14be,0xbef15aea,0xbf61c598,
0x3f800000,0x0,0x3f740bdd,0xbe9aa086,0x3f514d3d,0xbf13682a,0x3f1b02c6,0xbf4bbbf8,0x3f2c7cd4,0xbff10908,0x3d16c32c,0xbf7fd397,0xbe888e93,0xbf76ba07,0xbf0b9a6b,0xbf5695e5,
0x3f800000,0x0,0x3f731447,0xbea09ae5,0x3f4d9f02,0xbf187fc0,0x3f13682a,0xbf514d3d,0x3f14a031,0xbff4fa0b,0xbcc90ab0,0xbf7fec43,0xbeac7cd4,0xbf710908,0xbf1d7fd1,0xbf49d112,
0x3f800000,0x0,0x3f721352,0xbea68f12,0x3f49d112,0xbf1d7fd1,0x3f0b9a6b,0xbf5695e5,0x3ef8cfcc,0xbff853f8,0xbdafb680,0xbf7f0e58,0xbecf7bca,0xbf6a09a7,0xbf2e3bde,0xbf3b8f3b,
0x3f800000,0x0,0x3f710908,0xbeac7cd4,0x3f45e403,0xbf226799,0x3f039c3d,0xbf5b941a,0x3ec7c5c2,0xbffb14be,0xbe164083,0xbf7d3aac,0xbef15aea,0xbf61c598,0xbf3daef9,0xbf2beb4a,
0x3f800000,0x0,0x3f6ff573,0xbeb263ef,0x3f41d870,0xbf273656,0x3ef6e0cb,0xbf604621,0x3e964083,0xbffd3aac,0xbe541501,0xbf7a7302,0xbf08f59b,0xbf584853,0xbf4bbbf8,0xbf1b02c6,
0x3f800000,0x0,0x3f6ed89e,0xbeb8442a,0x3f3daef9,0xbf2beb4a,0x3ee63375,0xbf64aa59,0x3e48bd36,0xbffec46d,0xbe888e93,0xbf76ba07,0xbf187fc0,0xbf4d9f02,0xbf584853,0xbf08f59b,
0x3f800000,0x0,0x3f6db293,0xbebe1d4a,0x3f396842,0xbf3085bb,0x3ed53641,0xbf68bf3c,0x3dc8fb30,0xbfffb10f,0xbea68f12,0xbf721352,0xbf273656,0xbf41d870,0xbf633c5a,0xbeebcbbb,
0x3f800000,0x0,0x3f7fffb1,0xbb490fc6,0x3f7ffec4,0xbbc90f88,0x3f7ffd39,0xbc16cb58,0x3ffffb11,0xbcc90e90,0x3f7ff84a,0xbc7b514b,0x3f7ff4e6,0xbc96c9b6,0x3f7ff0e3,0xbcafea69,
0x3f800000,0x0,0x3f7ff84a,0xbc7b514b,0x3f7fe129,0xbcfb49ba,0x3f7fba9e,0xbd3c6dd5,0x3fff84ab,0xbdfb2b74,0x3f7f3f54,0xbd9cecf9,0x3f7eea9d,0xbdbc3ac3,0x3f7e868b,0xbddb7d37,
0x3f800000,0x0,0x3f7fe705,0xbce22a7a,0x3f7f9c18,0xbd621469,0x3f7f1f49,0xbda973ba,0x3ffe70b0,0xbe61bc2e,0x3f7d906e,0xbe0cec4a,0x3f7c7eb0,0xbe28defc,0x3f7b3bab,0xbe44b0b9,
0x3f800000,0x0,0x3f7fcbe2,0xbd2351cb,0x3f7f2f9d,0xbda3308c,0x3f7e2b72,0xbdf475c0,0x3ffcbfc9,0xbea2abb6,0x3f7aed37,0xbe4ada4f,0x3f78b47b,0xbe72b651,0x3f76167a,0xbe8d17c0,
0x3f800000,0x0,0x3f7fa6e3,0xbd55880e,0x3f7e9bc9,0xbdd53db9,0x3f7cdf6c,0xbe1f917b,0x3ffa7302,0xbed41501,0x3f77583a,0xbe840270,0x3f73913f,0xbe9d9e78,0x3f6f20b0,0xbeb6ccc3,
0x3f800000,0x0,0x3f7f7808,0xbd83db0a,0x3f7de0b1,0xbe039502,0x3f7b3bab,0xbe44b0b9,0x3ff78bc5,0xbf027dc0,0x3f72d4eb,0xbea21887,0x3f6d1c1d,0xbec1071e,0x3f666771,0xbedf28a9,
0x3f800000,0x0,0x3f7f3f54,0xbd9cecf9,0x3f7cfe73,0xbe1c76de,0x3f7940c0,0xbe698bba,0x3ff40bdd,0xbf1aa086,0x3f6d67a1,0xbebf926f,0x3f655e0b,0xbee363fa,0x3f5bfb34,0xbf02ef9f,
0x3f800000,0x0,0x3f7efcc9,0xbdb5f8da,0x3f7bf531,0xbe354098,0x3f76ef5b,0xbe870ada,0x3feff573,0xbf3263ef,0x3f671599,0xbedc53c1,0x3f5c61c7,0xbf0242b1,0x3f4fefa8,0xbf1553b7,
0x3f800000,0x0,0x3f7eb069,0xbdcefdb7,0x3f7ac516,0xbe4dee60,0x3f74484b,0xbe9920fe,0x3feb4b0c,0xbf49b953,0x3f5fe4e9,0xbef840c8,0x3f5233c6,0xbf121eb0,0x3f425b89,0xbf269de3,
0x3f800000,0x0,0x3f7e5a38,0xbde7fa9a,0x3f796e4e,0xbe667c66,0x3f714c7a,0xbeab0201,0x3fe60f88,0xbf60924f,0x3f57dc7f,0xbf099f4e,0x3f46e22a,0xbf212ff9,0x3f33587a,0xbf36ad7f,
0x3f800000,0x0,0x3f7dfa38,0xbe007745,0x3f77f110,0xbe7ee6e1,0x3f6dfcf2,0xbebca7af,0x3fe04621,0xbf76e0cb,0x3f4f0417,0xbf16999f,0x3f3a7ca4,0xbf2f61a5,0x3f2302d3,0xbf456439,
0x3f800000,0x0,0x3f7d906e,0xbe0cec4a,0x3f764d97,0xbe8b9507,0x3f6a5ad9,0xbece0bea,0x3fd9f26a,0xbf864b82,0x3f456439,0xbf2302d3,0x3f2d1469,0xbf3ca003,0x3f11796b,0xbf52a649,
0x3f800000,0x0,0x3f7d1cdd,0xbe195be0,0x3f748422,0xbe97a117,0x3f666771,0xbedf28a9,0x3fd31849,0xbf90d3cd,0x3f3b0629,0xbf2ecef7,0x3f1ebc12,0xbf48d8b3,0x3efdbabb,0xbf5e5aa6,
0x3f800000,0x0,0x3f7c9f8a,0xbe25c58c,0x3f7294f8,0xbea395c5,0x3f62241a,0xbeeff7fb,0x3fcbbbf8,0xbf9b02c6,0x3f2ff3e6,0xbf39f2ac,0x3f0f8784,0xbf53fac3,0x3ed6a399,0xbf686b39,
0x3f800000,0x0,0x3f7c187a,0xbe3228d4,0x3f708066,0xbeaf713a,0x3f5d924d,0xbf003a06,0x3fc3e200,0xbfa4d225,0x3f24381a,0xbf446337,0x3eff17b2,0xbf5df6be,0x3eadf73c,0xbf70c501,
0x3f800000,0x0,0x3f7b87b2,0xbe3e853e,0x3f6e46be,0xbebb31a0,0x3f58b3a1,0xbf084b92,0x3fbb8f3b,0xbfae3bde,0x3f17de12,0xbf4e1689,0x3eddbe79,0xbf66becc,0x3e840270,0xbf77583a,
0x3f800000,0x0,0x3f7aed37,0xbe4ada4f,0x3f6be858,0xbec6d529,0x3f5389c7,0xbf102dd5,0x3fb2c8c9,0xbfb73a23,0x3f0af1b7,0xbf570348,0x3ebb31a0,0xbf6e46be,0x3e3228d4,0xbf7c187a,
0x3f800000,0x0,0x3f7a4910,0xbe57278f,0x3f696591,0xbed25a09,0x3f4e1689,0xbf17de12,0x3fa99415,0xbfbfc767,0x3efafef7,0xbf5f20db,0x3e97a117,0xbf748422,0x3db5f8da,0xbf7efcc9,
0x3f800000,0x0,0x3f799b43,0xbe636c83,0x3f66becc,0xbeddbe79,0x3f485bca,0xbf1f599f,0x3f9ff6cb,0xbfc7de65,0x3edf28a9,0xbf666771,0x3e667c66,0xbf796e4e,0x3b490fc6,0xbf7fffb1,
0x3f800000,0x0,0x3f78e3d6,0xbe6fa8b2,0x3f63f473,0xbee900b7,0x3f425b89,0xbf269de3,0x3f95f6d9,0xbfcf7a1f,0x3ec27b55,0xbf6cd007,0x3e1c76de,0xbf7cfe73,0xbda973ba,0xbf7f1f49,
0x3f800000,0x0,0x3f7822d1,0xbe7bdba4,0x3f6106f2,0xbef41f07,0x3f3c17d9,0xbf2da859,0x3f8b9a6b,0xbfd695e5,0x3ea5129f,0xbf725470,0x3da3308c,0xbf7f2f9d,0xbe2bf804,0xbf7c5d3a,
0x3f800000,0x0,0x3f77583a,0xbe840270,0x3f5df6be,0xbeff17b2,0x3f3592e7,0xbf34768f,0x3f80e7e4,0xbfdd2d53,0x3e870ada,0xbf76ef5b,0x3bc90f88,0xbf7ffec4,0xbe80f8c0,0xbf77beb7,
0x3f800000,0x0,0x3f76841b,0xbe8a11f7,0x3f5ac450,0xbf04f484,0x3f2ecef7,0xbf3b0629,0x3f6bcbbb,0xbfe33c5a,0x3e5101f1,0xbf7a9c59,0xbd8a200a,0xbf7f6ac7,0xbeab0201,0xbf714c7a,
0x3f800000,0x0,0x3f75a67b,0xbe901c2c,0x3f577026,0xbf0a48ad,0x3f27ce61,0xbf4154e1,0x3f553641,0xbfe8bf3c,0x3e1324ca,0xbf7d57de,0xbe1008b7,0xbf7d7474,0xbed3c867,0xbf6912ae,
0x3f800000,0x0,0x3f74bf62,0xbe9620d2,0x3f53fac3,0xbf0f8784,0x3f209393,0xbf476085,0x3f3e1d4a,0xbfedb293,0x3da973ba,0xbf7f1f49,0xbe5a3997,0xbf7a1e84,0xbefafef7,0xbf5f20db,
0x3f800000,0x0,0x3f73ced9,0xbe9c1faf,0x3f5064af,0xbf14b039,0x3f19210f,0xbf4d26fd,0x3f268f12,0xbff21352,0x3cafea69,0xbf7ff0e3,0xbe919ddd,0xbf756d97,0xbf102dd5,0xbf5389c7,
0x3f800000,0x0,0x3f72d4eb,0xbea21887,0x3f4cae79,0xbf19c200,0x3f11796b,0xbf52a649,0x3f0e9a22,0xbff5dec6,0xbd2351cb,0xbf7fcbe2,0xbeb554ec,0xbf6f6830,0xbf21cbfb,0xbf466354,
0x3f800000,0x0,0x3f71d19f,0xbea80b1f,0x3f48d8b3,0xbf1ebc12,0x3f099f4e,0xbf57dc7f,0x3eec9a7f,0xbff91298,0xbdcefdb7,0xbf7eb069,0xbed8106b,0xbf6816a8,0xbf3238aa,0xbf37c655,
0x3f800000,0x0,0x3f70c501,0xbeadf73c,0x3f44e3f5,0xbf239da9,0x3f019573,0xbf5cc7d1,0x3ebb6ecf,0xbffbaccd,0xbe25c58c,0xbf7c9f8a,0xbef9a02d,0xbf5f8327,0xbf4154e1,0xbf27ce61,
0x3f800000,0x0,0x3f6faf1b,0xbeb3dca5,0x3f40d0da,0xbf286605,0x3ef2bd43,0xbf61668a,0x3e89cf86,0xbffdabcc,0xbe636c83,0xbf799b43,0xbf0cead0,0xbf55b993,0xbf4f0417,0xbf16999f,
0x3f800000,0x0,0x3f6e8ff8,0xbeb9bb1e,0x3f3ca003,0xbf2d1469,0x3ee1fb6a,0xbf65b710,0x3e2fb680,0xbfff0e58,0xbe901c2c,0xbf75a67b,0xbf1c420c,0xbf4ac77f,0xbf5b2c79,0xbf044889,
0x3f800000,0x0,0x3f6d67a1,0xbebf926f,0x3f385216,0xbf31a81d,0x3ed0eb2a,0xbf69b7e4,0x3d96c32c,0xbfffd397,0xbeadf73c,0xbf70c501,0xbf2ac082,0xbf3ebc1b,0xbf65b710,0xbee1fb6a,
0x3f800000,0x0,0x3f7ffec4,0xbbc90f88,0x3f7ffb11,0xbc490e90,0x3f7ff4e6,0xbc96c9b6,0x3fffec43,0xbd490ab0,0x3f7fe129,0xbcfb49ba,0x3f7fd397,0xbd16c32c,0x3f7fc38f,0xbd2fe007,
0x3f800000,0x0,0x3f7ff4e6,0xbc96c9b6,0x3f7fd397,0xbd16c32c,0x3f7f9c18,0xbd621469,0x3fff4e6d,0xbe16a905,0x3f7eea9d,0xbdbc3ac3,0x3f7e70b0,0xbde1bc2e,0x3f7de0b1,0xbe039502,
0x3f800000,0x0,0x3f7fe129,0xbcfb49ba,0x3f7f84ab,0xbd7b2b74,0x3f7eea9d,0xbdbc3ac3,0x3ffe1324,0xbe7ab273,0x3f7cfe73,0xbe1c76de,0x3f7baccd,0xbe3b6ecf,0x3f7a1e84,0xbe5a3997,
0x3f800000,0x0,0x3f7fc38f,0xbd2fe007,0x3f7f0e58,0xbdafb680,0x3f7de0b1,0xbe039502,0x3ffc3b28,0xbeaf10a2,0x3f7a1e84,0xbe5a3997,0x3f778bc5,0xbe827dc0,0x3f748422,0xbe97a117,
0x3f800000,0x0,0x3f7f9c18,0xbd621469,0x3f7e70b0,0xbde1bc2e,0x3f7c7eb0,0xbe28defc,0x3ff9c79d,0xbee05c13,0x3f764d97,0xbe8b9507,0x3f721352,0xbea68f12,0x3f6d1c1d,0xbec1071e,
0x3f800000,0x0,0x3f7f6ac7,0xbd8a200a,0x3f7dabcc,0xbe09cf86,0x3f7ac516,0xbe4dee60,0x3ff6ba07,0xbf088e93,0x3f718f57,0xbea986c4,0x3f6b4b0c,0xbec9b953,0x3f63f473,0xbee900b7,
0x3f800000,0x0,0x3f7f2f9d,0xbda3308c,0x3f7cbfc9,0xbe22abb6,0x3f78b47b,0xbe72b651,0x3ff31447,0xbf209ae5,0x3f6be858,0xbec6d529,0x3f633c5a,0xbeebcbbb,0x3f591e6a,0xbf07a136,
0x3f800000,0x0,0x3f7eea9d,0xbdbc3ac3,0x3f7baccd,0xbe3b6ecf,0x3f764d97,0xbe8b9507,0x3feed89e,0xbf38442a,0x3f655e0b,0xbee363fa,0x3f59f26a,0xbf064b82,0x3f4cae79,0xbf19c200,
0x3f800000,0x0,0x3f7e9bc9,0xbdd53db9,0x3f7a7302,0xbe541501,0x3f73913f,0xbe9d9e78,0x3fea09a7,0xbf4f7bca,0x3f5df6be,0xbeff17b2,0x3f4f7a1f,0xbf15f6d9,0x3f3ebc1b,0xbf2ac082,
0x3f800000,0x0,0x3f7e4323,0xbdee3876,0x3f791298,0xbe6c9a7f,0x3f708066,0xbeaf713a,0x3fe4aa59,0xbf663375,0x3f55b993,0xbf0cead0,0x3f43e200,0xbf24d225,0x3f2f61a5,0xbf3a7ca4,
0x3f800000,0x0,0x3f7de0b1,0xbe039502,0x3f778bc5,0xbe827dc0,0x3f6d1c1d,0xbec1071e,0x3fdebe05,0xbf7c5d27,0x3f4cae79,0xbf19c200,0x3f373a23,0xbf32c8c9,0x3f1ebc12,0xbf48d8b3,
0x3f800000,0x0,0x3f7d7474,0xbe1008b7,0x3f75dec6,0xbe8e9a22,0x3f696591,0xbed25a09,0x3fd84853,0xbf88f59b,0x3f42de29,0xbf26050a,0x3f299415,0xbf3fc767,0x3f0cead0,0xbf55b993,
0x3f800000,0x0,0x3f7cfe73,0xbe1c76de,0x3f740bdd,0xbe9aa086,0x3f655e0b,0xbee363fa,0x3fd14d3d,0xbf93682a,0x3f385216,0xbf31a81d,0x3f1b02c6,0xbf4bbbf8,0x3ef41f07,0xbf6106f2,
0x3f800000,0x0,0x3f7c7eb0,0xbe28defc,0x3f721352,0xbea68f12,0x3f6106f2,0xbef41f07,0x3fc9d112,0xbf9d7fd1,0x3f2d1469,0xbf3ca003,0x3f0b9a6b,0xbf5695e5,0x3ecc9b8b,0xbf6aab7b,
0x3f800000,0x0,0x3f7bf531,0xbe354098,0x3f6ff573,0xbeb263ef,0x3f5c61c7,0xbf0242b1,0x3fc1d870,0xbfa73656,0x3f212ff9,0xbf46e22a,0x3ef6e0cb,0xbf604621,0x3ea395c5,0xbf7294f8,
0x3f800000,0x0,0x3f7b61fc,0xbe419b37,0x3f6db293,0xbebe1d4a,0x3f577026,0xbf0a48ad,0x3fb96842,0xbfb085bb,0x3f14b039,0xbf5064af,0x3ed53641,0xbf68bf3c,0x3e72b651,0xbf78b47b,
0x3f800000,0x0,0x3f7ac516,0xbe4dee60,0x3f6b4b0c,0xbec9b953,0x3f5233c6,0xbf121eb0,0x3fb085bb,0xbfb96842,0x3f07a136,0xbf591e6a,0x3eb263ef,0xbf6ff573,0x3e1c76de,0xbf7cfe73,
0x3f800000,0x0,0x3f7a1e84,0xbe5a3997,0x3f68bf3c,0xbed53641,0x3f4cae79,0xbf19c200,0x3fa73656,0xbfc1d870,0x3ef41f07,0xbf6106f2,0x3e8e9a22,0xbf75dec6,0x3d8a200a,0xbf7f6ac7,
0x3f800000,0x0,0x3f796e4e,0xbe667c66,0x3f660f88,0xbee0924f,0x3f46e22a,0xbf212ff9,0x3f9d7fd1,0xbfc9d112,0x3ed8106b,0xbf6816a8,0x3e541501,0xbf7a7302,0xbc96c9b6,0xbf7ff4e6,
0x3f800000,0x0,0x3f78b47b,0xbe72b651,0x3f633c5a,0xbeebcbbb,0x3f40d0da,0xbf286605,0x3f93682a,0xbfd14d3d,0x3ebb31a0,0xbf6e46be,0x3e09cf86,0xbf7dabcc,0xbdd53db9,0xbf7e9bc9,
0x3f800000,0x0,0x3f77f110,0xbe7ee6e1,0x3f604621,0xbef6e0cb,0x3f3a7ca4,0xbf2f61a5,0x3f88f59b,0xbfd84853,0x3e9d9e78,0xbf73913f,0x3d7b2b74,0xbf7f84ab,0xbe419b37,0xbf7b61fc,
0x3f800000,0x0,0x3f772417,0xbe8586ce,0x3f5d2d53,0xbf00e7e4,0x3f33e7bc,0xbf36206c,0x3f7c5d27,0xbfdebe05,0x3e7ee6e1,0xbf77f110,0xbc490e90,0xbf7ffb11,0xbe8b9507,0xbf764d97,
0x3f800000,0x0,0x3f764d97,0xbe8b9507,0x3f59f26a,0xbf064b82,0x3f2d1469,0xbf3ca003,0x3f663375,0xbfe4aa59,0x3e419b37,0xbf7b61fc,0xbdafb680,0xbf7f0e58,0xbeb554ec,0xbf6f6830,
0x3f800000,0x0,0x3f756d97,0xbe919ddd,0x3f5695e5,0xbf0b9a6b,0x3f26050a,0xbf42de29,0x3f4f7bca,0xbfea09a7,0x3e039502,0xbf7de0b1,0xbe22abb6,0xbf7cbfc9,0xbeddbe79,0xbf66becc,
0x3f800000,0x0,0x3f748422,0xbe97a117,0x3f531849,0xbf10d3cd,0x3f1ebc12,0xbf48d8b3,0x3f38442a,0xbfeed89e,0x3d8a200a,0xbf7f6ac7,0xbe6c9a7f,0xbf791298,0xbf0242b1,0xbf5c61c7,
0x3f800000,0x0,0x3f73913f,0xbe9d9e78,0x3f4f7a1f,0xbf15f6d9,0x3f173c07,0xbf4e8d90,0x3f209ae5,0xbff31447,0x3bc90f88,0xbf7ffec4,0xbe9aa086,0xbf740bdd,0xbf14b039,0xbf5064af,
0x3f800000,0x0,0x3f7294f8,0xbea395c5,0x3f4bbbf8,0xbf1b02c6,0x3f0f8784,0xbf53fac3,0x3f088e93,0xbff6ba07,0xbd621469,0xbf7f9c18,0xbebe1d4a,0xbf6db293,0xbf26050a,0xbf42de29,
0x3f800000,0x0,0x3f718f57,0xbea986c4,0x3f47de65,0xbf1ff6cb,0x3f07a136,0xbf591e6a,0x3ee05c13,0xbff9c79d,0xbdee3876,0xbf7e4323,0xbee0924f,0xbf660f88,0xbf36206c,0xbf33e7bc,
0x3f800000,0x0,0x3f708066,0xbeaf713a,0x3f43e200,0xbf24d225,0x3eff17b2,0xbf5df6be,0x3eaf10a2,0xbffc3b28,0xbe354098,0xbf7bf531,0xbf00e7e4,0xbf5d2d53,0xbf44e3f5,0xbf239da9,
0x3f800000,0x0,0x3f6f6830,0xbeb554ec,0x3f3fc767,0xbf299415,0x3eee9479,0xbf628210,0x3e7ab273,0xbffe1324,0xbe72b651,0xbf78b47b,0xbf10d3cd,0xbf531849,0xbf5233c6,0xbf121eb0,
0x3f800000,0x0,0x3f6e46be,0xbebb31a0,0x3f3b8f3b,0xbf2e3bde,0x3eddbe79,0xbf66becc,0x3e16a905,0xbfff4e6d,0xbe97a117,0xbf748422,0xbf1ff6cb,0xbf47de65,0xbf5df6be,0xbeff17b2,
0x3f800000,0x0,0x3f6d1c1d,0xbec1071e,0x3f373a23,0xbf32c8c9,0x3ecc9b8b,0xbf6aab7b,0x3d490ab0,0xbfffec43,0xbeb554ec,0xbf6f6830,0xbf2e3bde,0xbf3b8f3b,0xbf6816a8,0xbed8106b,
0x3f800000,0x0,0x3f7ffd39,0xbc16cb58,0x3f7ff4e6,0xbc96c9b6,0x3f7fe705,0xbce22a7a,0x3fffd397,0xbd96c32c,0x3f7fba9e,0xbd3c6dd5,0x3f7f9c18,0xbd621469,0x3f7f7808,0xbd83db0a,
0x3f800000,0x0,0x3f7ff0e3,0xbcafea69,0x3f7fc38f,0xbd2fe007,0x3f7f7808,0xbd83db0a,0x3fff0e58,0xbe2fb680,0x3f7e868b,0xbddb7d37,0x3f7de0b1,0xbe039502,0x3f7d1cdd,0xbe195be0,
0x3f800000,0x0,0x3f7fdaaf,0xbd0a342f,0x3f7f6ac7,0xbd8a200a,0x3f7eb069,0xbdcefdb7,0x3ffdabcc,0xbe89cf86,0x3f7c5d3a,0xbe2bf804,0x3f7ac516,0xbe4dee60,0x3f78e3d6,0xbe6fa8b2,
0x3f800000,0x0,0x3f7fba9e,0xbd3c6dd5,0x3f7eea9d,0xbdbc3ac3,0x3f7d906e,0xbe0cec4a,0x3ffbaccd,0xbebb6ecf,0x3f7940c0,0xbe698bba,0x3f764d97,0xbe8b9507,0x3f72d4eb,0xbea21887,
0x3f800000,0x0,0x3f7f90b1,0xbd6ea038,0x3f7e4323,0xbdee3876,0x3f7c187a,0xbe3228d4,0x3ff91298,0xbeec9a7f,0x3f75341d,0xbe931f35,0x3f708066,0xbeaf713a,0x3f6afb8c,0xbecb2aae,
0x3f800000,0x0,0x3f7f5ce9,0xbd9064b4,0x3f7d7474,0xbe1008b7,0x3f7a4910,0xbe57278f,0x3ff5dec6,0xbf0e9a22,0x3f703b37,0xbeb0eacb,0x3f696591,0xbed25a09,0x3f61668a,0xbef2bd43,
0x3f800000,0x0,0x3f7f1f49,0xbda973ba,0x3f7c7eb0,0xbe28defc,0x3f7822d1,0xbe7bdba4,0x3ff21352,0xbf268f12,0x3f6a5ad9,0xbece0bea,0x3f6106f2,0xbef41f07,0x3f5627fe,0xbf0c42c9,
0x3f800000,0x0,0x3f7ed7d4,0xbdc27c39,0x3f7b61fc,0xbe419b37,0x3f75a67b,0xbe901c2c,0x3fedb293,0xbf3e1d4a,0x3f6398ac,0xbeea6681,0x3f577026,0xbf0a48ad,0x3f495521,0xbf1e1e22,
0x3f800000,0x0,0x3f7e868b,0xbddb7d37,0x3f7a1e84,0xbe5a3997,0x3f72d4eb,0xbea21887,0x3fe8bf3c,0xbf553641,0x3f5bfb34,0xbf02ef9f,0x3f4cae79,0xbf19c200,0x3f3b0629,0xbf2ecef7,
0x3f800000,0x0,0x3f7e2b72,0xbdf475c0,0x3f78b47b,0xbe72b651,0x3f6faf1b,0xbeb3dca5,0x3fe33c5a,0xbf6bcbbb,0x3f5389c7,0xbf102dd5,0x3f40d0da,0xbf286605,0x3f2b561b,0xbf3e35c5,
0x3f800000,0x0,0x3f7dc68c,0xbe06b26e,0x3f772417,0xbe8586ce,0x3f6c3624,0xbec5625c,0x3fdd2d53,0xbf80e7e4,0x3f4a4c87,0xbf1ce11f,0x3f33e7bc,0xbf36206c,0x3f1a6293,0xbf4c3578,
0x3f800000,0x0,0x3f7d57de,0xbe1324ca,0x3f756d97,0xbe919ddd,0x3f686b39,0xbed6a399,0x3fd695e5,0xbf8b9a6b,0x3f404c5c,0xbf28fd41,0x3f26050a,0xbf42de29,0x3f084b92,0xbf58b3a1,
0x3f800000,0x0,0x3f7cdf6c,0xbe1f917b,0x3f73913f,0xbe9d9e78,0x3f644fac,0xbee79a5d,0x3fcf7a1f,0xbf95f6d9,0x3f3592e7,0xbf34768f,0x3f173c07,0xbf4e8d90,0x3eea6681,0xbf6398ac,
0x3f800000,0x0,0x3f7c5d3a,0xbe2bf804,0x3f718f57,0xbea986c4,0x3f5fe4e9,0xbef840c8,0x3fc7de65,0xbf9ff6cb,0x3f2a2a80,0xbf3f41fc,0x3f07a136,0xbf591e6a,0x3ec27b55,0xbf6cd007,
0x3f800000,0x0,0x3f7bd14d,0xbe3857ec,0x3f6f6830,0xbeb554ec,0x3f5b2c79,0xbf044889,0x3fbfc767,0xbfa99415,0x3f1e1e22,0xbf495521,0x3eee9479,0xbf628210,0x3e9920fe,0xbf74484b,
0x3f800000,0x0,0x3f7b3bab,0xbe44b0b9,0x3f6d1c1d,0xbec1071e,0x3f5627fe,0xbf0c42c9,0x3fb73a23,0xbfb2c8c9,0x3f11796b,0xbf52a649,0x3ecc9b8b,0xbf6aab7b,0x3e5d4b1a,0xbf79f35e,
0x3f800000,0x0,0x3f7a9c59,0xbe5101f1,0x3f6aab7b,0xbecc9b8b,0x3f50d937,0xbf140c5f,0x3fae3bde,0xbfbb8f3b,0x3f044889,0xbf5b2c79,0x3ea986c4,0xbf718f57,0x3e06b26e,0xbf7dc68c,
0x3f800000,0x0,0x3f79f35e,0xbe5d4b1a,0x3f6816a8,0xbed8106b,0x3f4b41fa,0xbf1ba299,0x3fa4d225,0xbfc3e200,0x3eed3063,0xbf62df7b,0x3e8586ce,0xbf772417,0x3d3c6dd5,0xbf7fba9e,
0x3f800000,0x0,0x3f7940c0,0xbe698bba,0x3f655e0b,0xbee363fa,0x3f456439,0xbf2302d3,0x3f9b02c6,0xbfcbbbf8,0x3ed0eb2a,0xbf69b7e4,0x3e419b37,0xbf7b61fc,0xbd2351cb,0xbf7fcbe2,
0x3f800000,0x0,0x3f788486,0xbe75c35a,0x3f628210,0xbeee9479,0x3f3f41fc,0xbf2a2a80,0x3f90d3cd,0xbfd31849,0x3eb3dca5,0xbf6faf1b,0x3dee3876,0xbf7e4323,0xbe007745,0xbf7dfa38,
0x3f800000,0x0,0x3f77beb7,0xbe80f8c0,0x3f5f8327,0xbef9a02d,0x3f38dd65,0xbf311722,0x3f864b82,0xbfd9f26a,0x3e9620d2,0xbf74bf62,0x3d2fe007,0xbf7fc38f,0xbe57278f,0xbf7a4910,
0x3f800000,0x0,0x3f76ef5b,0xbe870ada,0x3f5c61c7,0xbf0242b1,0x3f3238aa,0xbf37c655,0x3f76e0cb,0xbfe04621,0x3e6fa8b2,0xbf78e3d6,0xbcfb49ba,0xbf7fe129,0xbe9620d2,0xbf74bf62,
0x3f800000,0x0,0x3f76167a,0xbe8d17c0,0x3f591e6a,0xbf07a136,0x3f2b561b,0xbf3e35c5,0x3f60924f,0xbfe60f88,0x3e3228d4,0xbf7c187a,0xbdd53db9,0xbf7e9bc9,0xbebf926f,0xbf6d67a1,
0x3f800000,0x0,0x3f75341d,0xbe931f35,0x3f55b993,0xbf0cead0,0x3f24381a,0xbf446337,0x3f49b953,0xbfeb4b0c,0x3de7fa9a,0xbf7e5a38,0xbe354098,0xbf7bf531,0xbee79a5d,0xbf644fac,
0x3f800000,0x0,0x3f74484b,0xbe9920fe,0x3f5233c6,0xbf121eb0,0x3f1ce11f,0xbf4a4c87,0x3f3263ef,0xbfeff573,0x3d55880e,0xbf7fa6e3,0xbe7ee6e1,0xbf77f110,0xbf06f686,0xbf5988ad,
0x3f800000,0x0,0x3f73530e,0xbe9f1cdf,0x3f4e8d90,0xbf173c07,0x3f1553b7,0xbf4fefa8,0x3f1aa086,0xbff40bdd,0xbc16cb58,0xbf7ffd39,0xbea395c5,0xbf7294f8,0xbf19210f,0xbf4d26fd,
0x3f800000,0x0,0x3f725470,0xbea5129f,0x3f4ac77f,0xbf1c420c,0x3f0d9281,0xbf554aa4,0x3f027dc0,0xbff78bc5,0xbd9064b4,0xbf7f5ce9,0xbec6d529,0xbf6be858,0xbf2a2a80,0xbf3f41fc,
0x3f800000,0x0,0x3f714c7a,0xbeab0201,0x3f46e22a,0xbf212ff9,0x3f05a02c,0xbf5a5ba0,0x3ed41501,0xbffa7302,0xbe06b26e,0xbf7dc68c,0xbee900b7,0xbf63f473,0xbf39f2ac,0xbf2ff3e6,
0x3f800000,0x0,0x3f703b37,0xbeb0eacb,0x3f42de29,0xbf26050a,0x3efafef7,0xbf5f20db,0x3ea2abb6,0xbffcbfc9,0xbe44b0b9,0xbf7b3bab,0xbf04f484,0xbf5ac450,0xbf485bca,0xbf1f599f,
0x3f800000,0x0,0x3f6f20b0,0xbeb6ccc3,0x3f3ebc1b,0xbf2ac082,0x3eea6681,0xbf6398ac,0x3e61bc2e,0xbffe70b0,0xbe80f8c0,0xbf77beb7,0xbf14b039,0xbf5064af,0xbf554aa4,0xbf0d9281,
0x3f800000,0x0,0x3f6dfcf2,0xbebca7af,0x3f3a7ca4,0xbf2f61a5,0x3ed97cb9,0xbf67c187,0x3dfb2b74,0xbfff84ab,0xbe9f1cdf,0xbf73530e,0xbf239da9,0xbf44e3f5,0xbf60a6cf,0xbef58035,
0x3f800000,0x0,0x3f6cd007,0xbec27b55,0x3f36206c,0xbf33e7bc,0x3ec8477c,0xbf6b99fb,0x3cc90e90,0xbffffb11,0xbebca7af,0xbf6dfcf2,0xbf31a81d,0xbf385216,0xbf6a5ad9,0xbece0bea,
0x3f800000,0x0,0x0,0x0,0x0,0x0,0x0,0x0,0x0,0x0,0x0,0x0,0x0,0x0,0x0,0x0,
0x0,0x0,0x0,0x0,0x0,0x0,0x0,0x0,0x0,0x0,0x0,0x0,0x0,0x0,0x0,0x0,
0x0,0x0,0x3e000000,0xbf20dff7,0x3ed0c429,0x0,0x3e000000,0x3e61f78b,0x3e0a8bd4,0x0,0x3e000000,0x3d5413cd,0x3d5df9ad,0x0,0x3e000000,0x3cf043ab,
0x0,0x0,0x3e000000,0x3ccbafaf,0xbd5df9ad,0x0,0x3e000000,0x3cf043ab,0xbe0a8bd4,0x0,0x3e000000,0x3d5413cd,0xbed0c429,0x0,0x3e000000,0x3e61f78b,
0x0,0x0,0x0,0x0,0x3f000000,0x0,0x0,0x3f000000,0x0,0x0,0x0,0x0,0x0,0x0,0x0,0x0,
0x0,0x0,0x0,0x0,0x0,0x0,0x0,0x0,0x0,0x0,0x0,0x0,0x3f000000,0x0,0x0,0xbf000000,
0x0,0x0,0x3e000000,0xbe3f90c7,0xbe8b7e3f,0x0,0x3e000000,0xbeb641af,0x3ea73d75,0x0,0x3e000000,0x3e9a827a,0x3da61ad1,0x0,0x3e000000,0x3dd906bd,
0x0,0x0,0x3e000000,0x3dab0dc1,0xbda61ad1,0x0,0x3e000000,0x3dd906bd,0xbea73d75,0x0,0x3e000000,0x3e9a827a,0x3e8b7e3f,0x0,0x3e000000,0xbeb641af,
0x0,0x0,0x0,0x0,0x0,0x0,0x0,0x0,0x3f000000,0x0,0x0,0x3f000000,0x0,0x0,0x0,0x0,
0x0,0x0,0x0,0x0,0x0,0x0,0x0,0x0,0x3f000000,0x0,0x0,0xbf000000,0x0,0x0,0x0,0x0,
0x0,0x0,0x3e000000,0xbdab0dc1,0xbda61ad1,0x0,0x3e000000,0xbdd906bd,0xbea73d75,0x0,0x3e000000,0xbe9a827a,0x3e8b7e3f,0x0,0x3e000000,0x3eb641af,
0x0,0x0,0x3e000000,0x3e3f90c7,0xbe8b7e3f,0x0,0x3e000000,0x3eb641af,0x3ea73d75,0x0,0x3e000000,0xbe9a827a,0x3da61ad1,0x0,0x3e000000,0xbdd906bd,
0x0,0x0,0x0,0x0,0x0,0x0,0x0,0x0,0x0,0x0,0x0,0x0,0x3f000000,0x0,0x0,0x3f000000,
0x0,0x0,0x0,0x0,0x3f000000,0x0,0x0,0xbf000000,0x0,0x0,0x0,0x0,0x0,0x0,0x0,0x0,
0x0,0x0,0x3e000000,0xbccbafaf,0xbd5df9ad,0x0,0x3e000000,0xbcf043ab,0xbe0a8bd4,0x0,0x3e000000,0xbd5413cd,0xbed0c429,0x0,0x3e000000,0xbe61f78b,
0x0,0x0,0x3e000000,0x3f20dff7,0x3ed0c429,0x0,0x3e000000,0xbe61f78b,0x3e0a8bd4,0x0,0x3e000000,0xbd5413cd,0x3d5df9ad,0x0,0x3e000000,0xbcf043ab,
};

struct Params {
    const __nv_bfloat16 *wr, *wi, *lre, *lim, *ldt, *dsk;
    float* out;
};

struct cf { float x, y; };
#define YIELD() asm volatile("pmevent 1;")
#define YS 14
#define YIELD_S1() do { if (YS & 1) YIELD(); } while (0)
#define YIELD_S2() do { if (YS & 2) YIELD(); } while (0)
#define YIELD_S3() do { if (YS & 4) YIELD(); } while (0)
__device__ __forceinline__ uint32_t smem_u32(const void* p) { return (uint32_t)__cvta_generic_to_shared(p); }
__device__ __forceinline__ void mbar_init(uint32_t a, uint32_t c) { asm volatile("mbarrier.init.shared::cta.b64 [%0], %1;" ::"r"(a), "r"(c) : "memory"); }
__device__ __forceinline__ void mbar_expect_tx(uint32_t a, uint32_t b) { asm volatile("mbarrier.arrive.expect_tx.shared::cta.b64 _, [%0], %1;" ::"r"(a), "r"(b) : "memory"); }
__device__ __forceinline__ void mbar_arrive(uint32_t a) { asm volatile("mbarrier.arrive.shared::cta.b64 _, [%0];" ::"r"(a) : "memory"); }
__device__ __forceinline__ void warp_arrive(uint32_t a) {
    __syncwarp();
    asm volatile("{.reg .pred p; elect.sync _|p, 0xffffffff; @p mbarrier.arrive.shared::cta.b64 _, [%0];}" ::"r"(a) : "memory");
}
__device__ __forceinline__ uint32_t mbar_try(uint32_t a, uint32_t ph) {
    uint32_t ok;
    asm volatile("{.reg .pred p; mbarrier.try_wait.parity.shared::cta.b64 p, [%1], %2; selp.u32 %0, 1, 0, p;}" : "=r"(ok) : "r"(a), "r"(ph) : "memory");
    return ok;
}
__device__ __forceinline__ void mbar_wait(uint32_t a, uint32_t ph) {
    uint32_t ok, n = 0;
    do { ok = mbar_try(a, ph); } while (!ok && ++n < SPIN_LIMIT);
}
__device__ __forceinline__ void mbar_wait_fast(uint32_t a, uint32_t ph) { if (!mbar_try(a, ph)) mbar_wait(a, ph); }
__device__ __forceinline__ unsigned ld_rlx(const unsigned* p) { unsigned v; asm volatile("ld.relaxed.gpu.global.u32 %0, [%1];" : "=r"(v) : "l"(p) : "memory"); return v; }
__device__ __forceinline__ void wait_cnt(const unsigned* p, unsigned target) {
    unsigned n = 0;
    while ((int)(ld_rlx(p) - target) < 0 && ++n < SPIN_LIMIT) __nanosleep(20);
}
__device__ __forceinline__ void red_hint(unsigned* p) { asm volatile("red.relaxed.gpu.global.add.u32 [%0], 1;" ::"l"(p) : "memory"); }
__device__ __forceinline__ void fence_async_sm() { asm volatile("fence.proxy.async.shared::cta;" ::: "memory"); }
#define bar_sync(id, n) asm volatile("bar.sync %0, %1;" ::"n"(id), "n"(n) : "memory")
#define bar_arrive(id, n) asm volatile("bar.arrive %0, %1;" ::"n"(id), "n"(n) : "memory")
__device__ __forceinline__ bool elect_one() {
    uint32_t r;
    asm volatile("{.reg .pred p; elect.sync _|p, 0xffffffff; selp.u32 %0, 1, 0, p;}" : "=r"(r));
    return r != 0;
}

__device__ __forceinline__ void tma2d(uint32_t dst, const CUtensorMap* m, int c0, int c1, uint32_t bar) {
    asm volatile("cp.async.bulk.tensor.2d.shared::cluster.global.mbarrier::complete_tx::bytes [%0], [%1, {%3,%4}], [%2];" ::"r"(dst), "l"(m), "r"(bar), "r"(c0), "r"(c1) : "memory");
}
__device__ __forceinline__ void tma3d(uint32_t dst, const CUtensorMap* m, int c0, int c1, int c2, uint32_t bar) {
    asm volatile("cp.async.bulk.tensor.3d.shared::cluster.global.mbarrier::complete_tx::bytes [%0], [%1, {%3,%4,%5}], [%2];" ::"r"(dst), "l"(m), "r"(bar), "r"(c0), "r"(c1), "r"(c2) : "memory");
}
__device__ __forceinline__ void tma4d_mc(uint32_t dst, const CUtensorMap* m, int c0, int c1, int c2, int c3, uint32_t bar) {
    asm volatile("cp.async.bulk.tensor.4d.shared::cluster.global.mbarrier::complete_tx::bytes.multicast::cluster [%0], [%1, {%3,%4,%5,%6}], [%2], %7;" ::"r"(dst), "l"(m), "r"(bar), "r"(c0), "r"(c1), "r"(c2), "r"(c3), "h"((uint16_t)3) : "memory");
}
__device__ __forceinline__ void tma4d(uint32_t dst, const CUtensorMap* m, int c0, int c1, int c2, int c3, uint32_t bar) {
    asm volatile("cp.async.bulk.tensor.4d.shared::cluster.global.mbarrier::complete_tx::bytes [%0], [%1, {%3,%4,%5,%6}], [%2];" ::"r"(dst), "l"(m), "r"(bar), "r"(c0), "r"(c1), "r"(c2), "r"(c3) : "memory");
}
__device__ __forceinline__ void tma2d_st(const CUtensorMap* m, int c0, int c1, uint32_t src) {
    asm volatile("cp.async.bulk.tensor.2d.global.shared::cta.bulk_group [%0, {%2,%3}], [%1];" ::"l"(m), "r"(src), "r"(c0), "r"(c1) : "memory");
}
__device__ __forceinline__ void tma5d(uint32_t dst, const CUtensorMap* m, int c0, int c1, int c2, int c3, int c4, uint32_t bar) {
    asm volatile("cp.async.bulk.tensor.5d.shared::cluster.global.mbarrier::complete_tx::bytes [%0], [%1, {%3,%4,%5,%6,%7}], [%2];" ::"r"(dst), "l"(m), "r"(bar), "r"(c0), "r"(c1), "r"(c2), "r"(c3), "r"(c4) : "memory");
}
__device__ __forceinline__ void bulk_ld(uint32_t dst, const void* src, uint32_t n, uint32_t bar) {
    asm volatile("cp.async.bulk.shared::cluster.global.mbarrier::complete_tx::bytes [%0], [%1], %2, [%3];" ::"r"(dst), "l"(src), "r"(n), "r"(bar) : "memory");
}
__device__ __forceinline__ void bulk_st(void* dst, uint32_t src, uint32_t n) {
    asm volatile("cp.async.bulk.global.shared::cta.bulk_group [%0], [%1], %2;" ::"l"(dst), "r"(src), "r"(n) : "memory");
}
__device__ __forceinline__ void bulk_commit() { asm volatile("cp.async.bulk.commit_group;" ::: "memory"); }
__device__ __forceinline__ void bulk_wait_read() { asm volatile("cp.async.bulk.wait_group.read 0;" ::: "memory"); }
__device__ __forceinline__ void bulk_wait_all() { asm volatile("cp.async.bulk.wait_group 0;" ::: "memory"); }
__device__ __forceinline__ void stsm4(uint32_t a, uint32_t r0, uint32_t r1, uint32_t r2, uint32_t r3) {
    asm volatile("stmatrix.sync.aligned.m8n8.x4.shared.b16 [%0], {%1,%2,%3,%4};" ::"r"(a), "r"(r0), "r"(r1), "r"(r2), "r"(r3) : "memory");
}
__device__ __forceinline__ void sts128(uint32_t a, uint32_t r0, uint32_t r1, uint32_t r2, uint32_t r3) {
    asm volatile("st.shared.v4.b32 [%0], {%1,%2,%3,%4};" ::"r"(a), "r"(r0), "r"(r1), "r"(r2), "r"(r3) : "memory");
}
__device__ __forceinline__ void lds128f(uint32_t a, float& x, float& y, float& z, float& u) { asm volatile("ld.shared.v4.f32 {%0,%1,%2,%3}, [%4];" : "=f"(x), "=f"(y), "=f"(z), "=f"(u) : "r"(a) : "memory"); }
__device__ __forceinline__ cf lds_cf(uint32_t a) { cf v; asm volatile("ld.shared.v2.f32 {%0,%1}, [%2];" : "=f"(v.x), "=f"(v.y) : "r"(a) : "memory"); return v; }
__device__ __forceinline__ void stg128(const void* a, uint32_t r0, uint32_t r1, uint32_t r2, uint32_t r3) {
    asm volatile("st.global.v4.b32 [%0], {%1,%2,%3,%4};" ::"l"(a), "r"(r0), "r"(r1), "r"(r2), "r"(r3) : "memory");
}
__device__ __forceinline__ int fresh_lane() { int v; asm volatile("mov.u32 %0, %%laneid;" : "=r"(v)); return v; }
__device__ __forceinline__ uint32_t opaque32(uint32_t v) { asm volatile("" : "+r"(v)); return v; }
__device__ __forceinline__ const uint8_t* padd(const void* base, uint32_t off) {
    uint64_t r;
    asm("{.reg .u32 l, h; mov.b64 {l, h}, %1; add.cc.u32 l, l, %2; addc.u32 h, h, 0; mov.b64 %0, {l, h};}" : "=l"(r) : "l"(base), "r"(off));
    return (const uint8_t*)r;
}
template <int N, int STRIDE> __device__ __forceinline__ void ldtab(uint32_t (&v)[4 * N], uint32_t off) {
    const uint8_t* a = padd(g_tab, off);
#pragma unroll
    for (int i = 0; i < N; i++)
        asm volatile("ld.global.nc.v4.b32 {%0,%1,%2,%3}, [%4];" : "=r"(v[4 * i]), "=r"(v[4 * i + 1]), "=r"(v[4 * i + 2]), "=r"(v[4 * i + 3]) : "l"(a + i * STRIDE));
}
template <int STRIDE> __device__ __forceinline__ void ldtab_cf(cf (&t)[8], uint32_t off) {
    uint32_t v[16];
    ldtab<4, STRIDE>(v, off);
#pragma unroll
    for (int i = 0; i < 8; i++) t[i] = {__uint_as_float(v[2 * i]), __uint_as_float(v[2 * i + 1])};
}
__device__ __forceinline__ uint32_t lds16(uint32_t a) { uint32_t v; asm volatile("ld.shared.u16 %0, [%1];" : "=r"(v) : "r"(a)); return v; }
__device__ __forceinline__ unsigned get_epoch(uint32_t bars) {
    mbar_wait(bars + B_EP, 0);
    unsigned e;
    asm volatile("ld.shared.u32 %0, [%1];" : "=r"(e) : "r"(bars + B_EPOCH) : "memory");
    return e;
}
__device__ __forceinline__ void sts64(uint32_t a, uint32_t x, uint32_t y) { asm volatile("st.shared.v2.b32 [%0], {%1,%2};" ::"r"(a), "r"(x), "r"(y) : "memory"); }
__device__ __forceinline__ uint32_t pk(float lo, float hi) { uint32_t r; asm("cvt.rn.bf16x2.f32 %0, %1, %2;" : "=r"(r) : "f"(hi), "f"(lo)); return r; }
__device__ __forceinline__ float bf2f(unsigned short v) { return __uint_as_float((uint32_t)v << 16); }

__device__ __forceinline__ uint64_t mkdesc(uint32_t addr, uint32_t lbo, uint32_t sbo, uint32_t swz) {
    return (uint64_t)((addr & 0x3FFFF) >> 4) | ((uint64_t)(lbo >> 4) << 16) | ((uint64_t)(sbo >> 4) << 32) | ((uint64_t)swz << 62);
}
__device__ __forceinline__ uint64_t opaque(uint64_t v) { asm volatile("" : "+l"(v)); return v; }
__device__ __forceinline__ void wg_fence() { asm volatile("wgmma.fence.sync.aligned;" ::: "memory"); }
__device__ __forceinline__ void wg_commit() { asm volatile("wgmma.commit_group.sync.aligned;" ::: "memory"); }
template <int N> __device__ __forceinline__ void wg_wait() { asm volatile("wgmma.wait_group.sync.aligned %0;" ::"n"(N) : "memory"); }
template <int N> __device__ __forceinline__ void pin(float (&d)[N]) {
#pragma unroll
    for (int i = 0; i < N; i++) asm volatile("" : "+f"(d[i])::"memory");
}
template <int N> __device__ __forceinline__ void pinu(uint32_t (&d)[N]) {
#pragma unroll
    for (int i = 0; i < N; i++) asm volatile("" : "+r"(d[i])::"memory");
}

#define R8(d, o) "+f"(d[o]), "+f"(d[o + 1]), "+f"(d[o + 2]), "+f"(d[o + 3]), "+f"(d[o + 4]), "+f"(d[o + 5]), "+f"(d[o + 6]), "+f"(d[o + 7])
#define L8 "%0,%1,%2,%3,%4,%5,%6,%7"
#define L32 L8 ",%8,%9,%10,%11,%12,%13,%14,%15,%16,%17,%18,%19,%20,%21,%22,%23,%24,%25,%26,%27,%28,%29,%30,%31"
#define L56 L32 ",%32,%33,%34,%35,%36,%37,%38,%39,%40,%41,%42,%43,%44,%45,%46,%47,%48,%49,%50,%51,%52,%53,%54,%55"
#define L64 L56 ",%56,%57,%58,%59,%60,%61,%62,%63"

template <int O, int TA, int TB, int N> __device__ __forceinline__ void mma128_ss(float (&d)[N], uint64_t da, uint64_t db, int sc) {
    asm volatile("{.reg .pred p; setp.ne.b32 p, %66, 0;\n"
                 "wgmma.mma_async.sync.aligned.m64n128k16.f32.bf16.bf16 {" L64 "}, %64, %65, p, 1, 1, %67, %68;}"
                 : R8(d, O), R8(d, O + 8), R8(d, O + 16), R8(d, O + 24), R8(d, O + 32), R8(d, O + 40), R8(d, O + 48), R8(d, O + 56)
                 : "l"(da), "l"(db), "r"(sc), "n"(TA), "n"(TB));
}
template <int O, int TB> __device__ __forceinline__ void mma128_rs(float (&d)[128], uint32_t a0, uint32_t a1, uint32_t a2, uint32_t a3, uint64_t db, int sc) {
    asm volatile("{.reg .pred p; setp.ne.b32 p, %69, 0;\n"
                 "wgmma.mma_async.sync.aligned.m64n128k16.f32.bf16.bf16 {" L64 "}, {%64,%65,%66,%67}, %68, p, 1, 1, %70;}"
                 : R8(d, O), R8(d, O + 8), R8(d, O + 16), R8(d, O + 24), R8(d, O + 32), R8(d, O + 40), R8(d, O + 48), R8(d, O + 56)
                 : "r"(a0), "r"(a1), "r"(a2), "r"(a3), "l"(db), "r"(sc), "n"(TB));
}
template <int TB> __device__ __forceinline__ void mma64_rs(float (&d)[32], uint32_t a0, uint32_t a1, uint32_t a2, uint32_t a3, uint64_t db, int sc) {
    asm volatile("{.reg .pred p; setp.ne.b32 p, %37, 0;\n"
                 "wgmma.mma_async.sync.aligned.m64n64k16.f32.bf16.bf16 {" L32 "}, {%32,%33,%34,%35}, %36, p, 1, 1, %38;}"
                 : R8(d, 0), R8(d, 8), R8(d, 16), R8(d, 24)
                 : "r"(a0), "r"(a1), "r"(a2), "r"(a3), "l"(db), "r"(sc), "n"(TB));
}
__device__ __forceinline__ void mma112_ss(float (&d)[64], uint64_t da, uint64_t db, int sc) {
    asm volatile("{.reg .pred p; setp.ne.b32 p, %58, 0;\n"
                 "wgmma.mma_async.sync.aligned.m64n112k16.f32.bf16.bf16 {" L56 "}, %56, %57, p, 1, 1, 0, 1;}"
                 : R8(d, 8), R8(d, 16), R8(d, 24), R8(d, 32), R8(d, 40), R8(d, 48), R8(d, 56)
                 : "l"(da), "l"(db), "r"(sc));
}
__device__ __forceinline__ void mma16_rs(float (&d)[64], uint32_t a0, uint32_t a1, uint32_t a2, uint32_t a3, uint64_t db, int sc) {
    asm volatile("{.reg .pred p; setp.ne.b32 p, %13, 0;\n"
                 "wgmma.mma_async.sync.aligned.m64n16k16.f32.bf16.bf16 {" L8 "}, {%8,%9,%10,%11}, %12, p, 1, 1, 1;}"
                 : R8(d, 0)
                 : "r"(a0), "r"(a1), "r"(a2), "r"(a3), "l"(db), "r"(sc));
}

__device__ __forceinline__ cf cmul(cf a, cf b) { return {fmaf(a.x, b.x, -a.y * b.y), fmaf(a.x, b.y, a.y * b.x)}; }
__device__ __forceinline__ cf cmulc(cf a, cf b) { return {fmaf(a.x, b.x, a.y * b.y), fmaf(a.y, b.x, -a.x * b.y)}; }
__device__ __forceinline__ cf cfma(cf a, cf b, cf c) { return {fmaf(a.x, b.x, fmaf(-a.y, b.y, c.x)), fmaf(a.x, b.y, fmaf(a.y, b.x, c.y))}; }
__device__ __forceinline__ cf csq(cf a) { return {fmaf(a.x, a.x, -a.y * a.y), (a.x * a.y) * 2.f}; }
__device__ __forceinline__ cf csel(int c, cf a, cf b) {
    cf r;
    asm("{.reg .pred p; setp.ne.s32 p, %2, 0; selp.f32 %0, %3, %5, p; selp.f32 %1, %4, %6, p;}" : "=f"(r.x), "=f"(r.y) : "r"(c), "f"(a.x), "f"(a.y), "f"(b.x), "f"(b.y));
    return r;
}
__device__ __forceinline__ cf cadd(cf a, cf b) { return {a.x + b.x, a.y + b.y}; }
__device__ __forceinline__ cf csub(cf a, cf b) { return {a.x - b.x, a.y - b.y}; }
__device__ __forceinline__ cf twice_minus(cf a, cf s) { return {fmaf(2.f, a.x, -s.x), fmaf(2.f, a.y, -s.y)}; }
__device__ __forceinline__ cf twid(int m, int M) {
    int r = ((m + M / 2) & (M - 1)) - M / 2;
    float s, c;
    __sincosf((float)r * (-6.283185307179586f / (float)M), &s, &c);
    return {c, s};
}
struct c2 { cf a, b; };
#define YP1 2
#define YP3 3
template <int Y> __device__ __forceinline__ void fin(c2& u) { if (Y & 1) asm volatile("pmevent 1;" : "+f"(u.a.x), "+f"(u.a.y), "+f"(u.b.x), "+f"(u.b.y)); }
template <int Y> __device__ __forceinline__ void fin(c2& u, c2& v) {
    if (Y & 2) asm volatile("pmevent 1;" : "+f"(u.a.x), "+f"(u.a.y), "+f"(u.b.x), "+f"(u.b.y), "+f"(v.a.x), "+f"(v.a.y), "+f"(v.b.x), "+f"(v.b.y));
}
__device__ __forceinline__ c2 mul2(c2 u, cf t) { return {cmul(u.a, t), cmul(u.b, t)}; }
__device__ __forceinline__ c2 mul2(c2 u, c2 t) { return {cmul(u.a, t.a), cmul(u.b, t.b)}; }
__device__ __forceinline__ c2 fma2(c2 u, cf t, c2 c) { return {cfma(u.a, t, c.a), cfma(u.b, t, c.b)}; }
__device__ __forceinline__ c2 fma2(c2 u, c2 t, c2 c) { return {cfma(u.a, t.a, c.a), cfma(u.b, t.b, c.b)}; }
__device__ __forceinline__ c2 twm2(c2 u, c2 s) { return {twice_minus(u.a, s.a), twice_minus(u.b, s.b)}; }
template <int Y> __device__ __forceinline__ void bfly(c2& u, c2& v) { const c2 t = u; u = {cadd(t.a, v.a), cadd(t.b, v.b)}; v = {csub(t.a, v.a), csub(t.b, v.b)}; fin<Y>(u, v); }
template <int Y> __device__ __forceinline__ void bfly_mi(c2& u, c2& v) {
    const c2 t = u, z = v;
    u = {{t.a.x + z.a.y, t.a.y - z.a.x}, {t.b.x + z.b.y, t.b.y - z.b.x}};
    v = {{t.a.x - z.a.y, t.a.y + z.a.x}, {t.b.x - z.b.y, t.b.y + z.b.x}};
    fin<Y>(u, v);
}
template <int Y> __device__ __forceinline__ void bfly_s(c2& u, c2& v) {
    const float s = 0.70710678118654752f;
    const c2 t = u, z = v;
    u = {{fmaf(s, z.a.x, t.a.x), fmaf(s, z.a.y, t.a.y)}, {fmaf(s, z.b.x, t.b.x), fmaf(s, z.b.y, t.b.y)}};
    v = {{fmaf(-s, z.a.x, t.a.x), fmaf(-s, z.a.y, t.a.y)}, {fmaf(-s, z.b.x, t.b.x), fmaf(-s, z.b.y, t.b.y)}};
    fin<Y>(u, v);
}
template <int Y, class T> __device__ __forceinline__ void bfly_tw(c2& u0, c2& v0, T t0, c2& u1, c2& v1, T t1) {
    v0 = fma2(v0, t0, u0); fin<Y>(v0);
    v1 = fma2(v1, t1, u1); fin<Y>(v1);
    const c2 a = twm2(u0, v0), b = twm2(u1, v1);
    u0 = v0; u1 = v1; v0 = a; v1 = b;
    fin<Y>(v0, v1);
}
template <bool TW, int Y> __device__ __forceinline__ void dft8(c2 (&v)[8], const cf (&tw)[8]) {
    if (TW) {
#pragma unroll
        for (int n = 1; n < 4; n++) { v[n] = mul2(v[n], tw[n]); fin<Y>(v[n]); }
        bfly_tw<Y>(v[0], v[4], tw[4], v[2], v[6], tw[6]);
        bfly_tw<Y>(v[1], v[5], tw[5], v[3], v[7], tw[7]);
    } else {
#pragma unroll
        for (int n = 0; n < 4; n++) bfly<Y>(v[n], v[n + 4]);
    }
    bfly<Y>(v[0], v[2]); bfly_mi<Y>(v[4], v[6]);
    bfly<Y>(v[1], v[3]); bfly_mi<Y>(v[5], v[7]);
    v[5] = {{v[5].a.x + v[5].a.y, v[5].a.y - v[5].a.x}, {v[5].b.x + v[5].b.y, v[5].b.y - v[5].b.x}};
    v[7] = {{v[7].a.y - v[7].a.x, -v[7].a.x - v[7].a.y}, {v[7].b.y - v[7].b.x, -v[7].b.x - v[7].b.y}};
    fin<Y>(v[5], v[7]);
    bfly<Y>(v[0], v[1]); bfly_s<Y>(v[4], v[5]); bfly_mi<Y>(v[2], v[3]); bfly_s<Y>(v[6], v[7]);
    const c2 t1 = v[1], t3 = v[3];
    v[1] = v[4]; v[4] = t1; v[3] = v[6]; v[6] = t3;
}

__device__ __forceinline__ void gather(uint64_t (&fv)[4], const uint8_t* a, int n) {
    asm volatile("{.reg .pred p0, p1, p2, p3;\n"
                 "setp.ge.s32 p0, %5, 0; setp.ge.s32 p1, %5, 4; setp.ge.s32 p2, %5, 8; setp.ge.s32 p3, %5, 12;\n"
                 "@p0 ld.relaxed.gpu.global.b64 %0, [%4]; @p1 ld.relaxed.gpu.global.b64 %1, [%4+-32768];\n"
                 "@p2 ld.relaxed.gpu.global.b64 %2, [%4+-65536]; @p3 ld.relaxed.gpu.global.b64 %3, [%4+-98304];}"
                 : "+l"(fv[0]), "+l"(fv[1]), "+l"(fv[2]), "+l"(fv[3]) : "l"(a), "r"(n) : "memory");
}
__device__ __forceinline__ cf as_cf(uint64_t v) { cf r; asm("mov.b64 {%0,%1}, %2;" : "=f"(r.x), "=f"(r.y) : "l"(v)); return r; }
template <int H> __device__ __forceinline__ void prescale(float (&u)[64], const float (&d)[128], cf gam) {
#pragma unroll
    for (int i = 0; i < 32; i += 2) {
        const int r = 2 * i + 2 * H;
        c2 v = mul2(c2{{d[r], -d[64 + r]}, {d[r + 1], -d[65 + r]}}, gam);
        if (YS & 2) asm volatile("pmevent 1;" : "+f"(v.a.x), "+f"(v.a.y), "+f"(v.b.x), "+f"(v.b.y));
        u[i] = v.a.x; u[32 + i] = v.a.y; u[i + 1] = v.b.x; u[33 + i] = v.b.y;
    }
}
__device__ __forceinline__ void scan2(const float (&u)[64], cf lam, cf st, const uint8_t* hptr, uint32_t hm, uint32_t hb, uint32_t& keep) {
    uint32_t hp[32];
#pragma unroll
    for (int jj = 0; jj < 4; jj++) {
        cf v[8];
#pragma unroll
        for (int i = 0; i < 8; i++) v[i] = st = cfma(lam, st, {u[8 * jj + i], u[32 + 8 * jj + i]});
        const int o = 8 * jj;
        hp[o] = pk(v[0].x, v[2].x); hp[o + 1] = pk(v[4].x, v[6].x); hp[o + 2] = pk(v[1].x, v[3].x); hp[o + 3] = pk(v[5].x, v[7].x);
        hp[o + 4] = pk(v[0].y, v[2].y); hp[o + 5] = pk(v[4].y, v[6].y); hp[o + 6] = pk(v[1].y, v[3].y); hp[o + 7] = pk(v[5].y, v[7].y);
        hp[o + jj] = (hp[o + jj] & hm) | hb;
        hp[o + 4 + jj] = (hp[o + 4 + jj] & hm) | hb;
        stg128(hptr + (jj >> 1) * 8192 + (jj & 1) * 512, hp[o], hp[o + 1], hp[o + 2], hp[o + 3]);
        stg128(hptr + 16384 + (jj >> 1) * 8192 + (jj & 1) * 512, hp[o + 4], hp[o + 5], hp[o + 6], hp[o + 7]);
        YIELD_S3();
        if (jj > 0) {
#pragma unroll
            for (int i = o - 8; i < o; i += 2) asm volatile("lop3.b32 %0, %0, %1, %2, 0x80;" : "+r"(keep) : "r"(hp[i]), "r"(hp[i + 1]));
        }
    }
}

__device__ __forceinline__ int pos_of(int n) { return (n & 24) + 4 * (n & 1) + ((n >> 1) & 3); }
__device__ __forceinline__ int unit_of(int role, int u, int& slot) {
    const int g = role & 7, w = (role >> 3) & 3, b = role >> 5;
    slot = role >= 128 ? g : (g ? 16 * g + w + 4 * b : 4 * w + b);
    return role >= 128 ? 32 * max(2 * g + u, 1) : (g ? g + 16 * w : ((w & 1) << 4) + ((w & 2) << 2)) + 64 * b + 256 * u;
}
template <int STRIDE> __device__ __forceinline__ bool tags_ok(uint32_t a, uint32_t ep) {
    uint32_t v[4], ok;
#pragma unroll
    for (int i = 0; i < 4; i++) asm volatile("ld.shared.u32 %0, [%1];" : "=r"(v[i]) : "r"(a + i * STRIDE) : "memory");
    asm volatile("{.reg .pred p; .reg .b32 a, b; lop3.b32 a, %1, %2, %5, 0x7e; lop3.b32 b, %3, %4, %5, 0x7e; lop3.b32 a, a, b, 1, 0xa8;\n"
                 "setp.eq.u32 p, a, 0; vote.sync.all.pred p, p, -1; selp.u32 %0, 1, 0, p;}" : "=r"(ok) : "r"(v[0]), "r"(v[1]), "r"(v[2]), "r"(v[3]), "r"(ep));
    return ok;
}
__device__ __forceinline__ void load_w_rows(uint32_t dst, const CUtensorMap* mr, const CUtensorMap* mi, int kap, uint32_t bar) {
#pragma unroll 1
    for (int i = 0; i < 4; i++) {
        __nanosleep(200);
        if (elect_one()) {
            if (!i) mbar_expect_tx(bar, 16 * WPITCH);
            tma2d(dst + i * 4 * WPITCH, (i & 1) ? mi : mr, ((i < 2 ? kap : (512 - kap) & 511) * 1026 >> 4) * 2, 0, bar);
        }
    }
}
template <int K0, int K1> __device__ __forceinline__ void store_v(const uint32_t (&vo)[32], const uint8_t* vp, bool p) {
    if (p) {
#pragma unroll
        for (int k = K0; k < K1; k++)
            asm volatile("st.global.v2.b32 [%0], {%1,%2};" ::"l"(vp + (k >> 2) * (1 << 20) + ((k >> 1) & 1) * 8192 + (k & 1) * (4 * 32768)), "r"(vo[2 * k]), "r"(vo[2 * k + 1]) : "memory");
    }
}
#define SB0 1024
__device__ __forceinline__ uint64_t ring_desc(uint32_t sb, uint32_t off, uint32_t lbo, uint32_t swz) {
    uint64_t d;
    asm volatile("{.reg .b32 z; shr.u32 z, %1, 28; mov.b64 %0, {z, z}; add.u64 %0, %0, %2;}" : "=l"(d) : "r"(sb), "l"(mkdesc(SB0 + off, lbo, 1024, swz)));
    return d;
}
struct Ring {
    uint32_t full, rel;
    uint32_t n;
    bool sig;
};
__device__ __forceinline__ void ring_release(const Ring& r, uint32_t o) {
    if (r.sig) asm volatile("mbarrier.arrive.shared::cluster.b64 _, [%0];" ::"r"(r.rel + o) : "memory");
}
__device__ __forceinline__ void peek(uint32_t a, uint32_t ph) { asm volatile("mbarrier.test_wait.parity.shared::cta.b64 pk, [%0], %1;" ::"r"(a), "r"(ph) : "memory"); }
__device__ __forceinline__ void peek_wait(uint32_t a, uint32_t ph, uint32_t& n) {
    asm volatile("{@pk bra DONE;\n"
                 "LOOP: mbarrier.try_wait.parity.shared::cta.b64 pk, [%1], %2; add.u32 %0, %0, 1; setp.gt.or.u32 pk, %0, %3, pk; @!pk bra LOOP;\n"
                 "DONE: }" : "+r"(n) : "r"(a), "r"(ph), "n"(SPIN_LIMIT) : "memory");
}
#define SL(k) ((k) % NST)
#define PH(k) (((k) / NST) & 1)
#define H64 "%64,%65,%66,%67,%68,%69,%70,%71,%72,%73,%74,%75,%76,%77,%78,%79,%80,%81,%82,%83,%84,%85,%86,%87,%88,%89,%90,%91,%92,%93,%94,%95," \
            "%96,%97,%98,%99,%100,%101,%102,%103,%104,%105,%106,%107,%108,%109,%110,%111,%112,%113,%114,%115,%116,%117,%118,%119,%120,%121,%122,%123,%124,%125,%126,%127"
#define WG_MMA "wgmma.mma_async.sync.aligned.m64n128k16.f32.bf16.bf16 "
#define DESC_B(S, j) "mov.b64 {t, hb}, %130; mov.b64 db, {%137 + 2048 * " #S " + 2 * " #j ", hb};\n"
#define MMA_LO(S, j, p) "add.u64 da, %129, 2048 * " #S " + %136 * " #j ";" DESC_B(S, j) WG_MMA "{" L64 "}, da, db, " #p ", 1, 1, %138, 0;\n"
#define MMA_HI(S, j, p) "add.u64 da, %129, 2048 * " #S " + 512 + %136 * " #j ";\n" WG_MMA "{" H64 "}, da, db, " #p ", 1, 1, %138, 0;\n"
#define STEP(S, P, N, ph, pa, pr, X, Y) \
    "wgmma.fence.sync.aligned;\n" MMA_LO(S, 0, pa) MMA_HI(S, 0, pa) \
    "wgmma.commit_group.sync.aligned; wgmma.wait_group.sync.aligned 1; @" #pr " mbarrier.arrive.shared::cluster.b64 _, [%132 + 8 * " #P "];\n" MMA_LO(S, 1, 1) \
    "mbarrier.test_wait.parity.shared::cta.b64 pk, [%131 + 8 * " #N "], " #ph ";\n" MMA_HI(S, 1, 1) MMA_LO(S, 2, 1) X MMA_HI(S, 2, 1) MMA_LO(S, 3, 1) MMA_HI(S, 3, 1) \
    "wgmma.commit_group.sync.aligned;\n" P4A Y "@pk bra GO" #S ";\n" \
    "WAIT" #S ": mbarrier.try_wait.parity.shared::cta.b64 pk, [%131 + 8 * " #N "], " #ph "; add.u32 %128, %128, 1; setp.gt.or.u32 pk, %128, %139, pk; @!pk bra WAIT" #S ";\n" \
    "GO" #S ":\n" P4B
#define P4A
#define P4B
#define P4I
#define P4O
#define STEP_ARGS(TA) \
    : R8(d, 0), R8(d, 8), R8(d, 16), R8(d, 24), R8(d, 32), R8(d, 40), R8(d, 48), R8(d, 56), \
      R8(d, 64), R8(d, 72), R8(d, 80), R8(d, 88), R8(d, 96), R8(d, 104), R8(d, 112), R8(d, 120), "+r"(r.n) \
    : "l"(ha), "l"(hb), "r"(r.full), "r"(r.rel), "r"((uint32_t)r.sig), "r"(wg), \
      "n"(SB0 / 16 + (TA ? 32 << 16 : 1 << 16)), "n"(TA ? 128 : 2), "n"(SB0 / 16 + 1024 + (1 << 16)), "n"(TA), "n"(SPIN_LIMIT) P4O \
    : "memory"
#define STEP_REGS "{.reg .b32 k, t, ph, hb; .reg .b64 da, db; .reg .pred ps, pl, pa, pr;\n" P4I "setp.ne.u32 ps, %133, 0;\n"
#define FIRST_WAIT "FIRST: mbarrier.try_wait.parity.shared::cta.b64 pk, [t], ph; @pk bra START; add.u32 %128, %128, 1; setp.le.u32 pk, %128, %139; @pk bra FIRST; START:\n"
__device__ __forceinline__ void gemm1(float (&d)[128], Ring& r, uint64_t ha, uint64_t hb, int wg) {
    asm volatile(STEP_REGS "mul.lo.u32 k, %134, 15; mov.b32 ph, %134; setp.ne.u32 pl, k, 0; mad.lo.u32 t, %134, 8, %131;\n"
                 "pmevent 1; @pl bar.sync 1, 256;\n" FIRST_WAIT "@pl bra ONE;\n"
                 "LOOP: setp.ne.u32 pa, k, 0; and.pred pr, pa, ps; setp.eq.u32 pl, k, 15;\n"
                 STEP(0, 4, 1, ph, pa, pr, "@pl bar.arrive 1, 256;\n", "@pl bra END;\n")
                 "ONE: setp.ne.u32 pa, k, 15; and.pred pr, pa, ps; setp.eq.u32 pl, k, 30;\n"
                 STEP(1, 0, 2, ph, pa, pr, "@pl bar.arrive 2, 256;\n", "@pl bra END;\n")
                 STEP(2, 1, 3, ph, 1, ps, "", "") STEP(3, 2, 4, ph, 1, ps, "", "") "xor.b32 ph, ph, 1; add.u32 k, k, 5;\n" STEP(4, 3, 0, ph, 1, ps, "", "")
                 "bra LOOP;\n"
                 "END:\n" P4B "}" STEP_ARGS(0));
}
__device__ __forceinline__ void gemm2(float (&d)[128], Ring& r, uint64_t ha, uint64_t hb, int wg) {
    asm volatile(STEP_REGS "mov.b32 k, 0; mov.b32 ph, 0; add.u32 t, %131, 16;\n"
                 "pmevent 1; bar.sync 2, 256;\n" FIRST_WAIT
                 "LOOP: setp.ne.u32 pa, k, 0; and.pred pr, pa, ps; setp.eq.u32 pl, k, 5;\n"
                 STEP(2, 1, 3, ph, pa, pr, "", "") STEP(3, 2, 4, ph, 1, ps, "", "") "xor.b32 ph, ph, 1; add.u32 k, k, 1;\n" STEP(4, 3, 0, ph, 1, ps, "", "")
                 "@pl bra END;\n" STEP(0, 4, 1, ph, 1, ps, "", "") STEP(1, 0, 2, ph, 1, ps, "", "")
                 "bra LOOP;\n"
                 "END: }" STEP_ARGS(1));
}
template <int O, int K, int J> __device__ __forceinline__ void mma_h(float (&y)[128], uint64_t a, uint64_t b) { mma128_ss<O, 1, 0>(y, a + SL(K) * 2048 + O * 8 + 128 * J, b + SL(K) * 2048 + 2 * J, 1); }
template <int O, int K> __device__ __forceinline__ void half_step(float (&y)[128], uint64_t a, uint64_t b) { mma_h<O, K, 0>(y, a, b); mma_h<O, K, 1>(y, a, b); mma_h<O, K, 2>(y, a, b); mma_h<O, K, 3>(y, a, b); }
template <int R, int U> __device__ __forceinline__ void out_piece(float (&y)[128], const uint32_t (&dd)[16], uint32_t x0, uint32_t x1, float* op) {
    const int i = 64 * (R >> 1) + 8 * U + 2 * (R & 1);
    asm("mul.rn.bf16x2 %0, %0, %1;" : "+r"(x0) : "r"(dd[2 * U]));
    asm("mul.rn.bf16x2 %0, %0, %1;" : "+r"(x1) : "r"(dd[2 * U + 1]));
    asm volatile("st.global.v4.f32 [%0], {%1,%2,%3,%4};" ::"l"(op + (32 * (R & 1) + 16 * (R >> 1)) * 2048 + 16 * U),
                 "f"(y[i] + __uint_as_float(x0 << 16)), "f"(y[i + 1] + __uint_as_float(x0 & 0xffff0000u)),
                 "f"(y[i + 4] + __uint_as_float(x1 << 16)), "f"(y[i + 5] + __uint_as_float(x1 & 0xffff0000u)) : "memory");
}
template <int R, int U0> __device__ __forceinline__ void load_x4(uint32_t (&xx)[8], uint32_t xa) {
#pragma unroll
    for (int u = 0; u < 4; u++)
        asm volatile("ld.shared.v2.b32 {%0,%1}, [%2];" : "=r"(xx[2 * u]), "=r"(xx[2 * u + 1]) : "r"((xa ^ (u << 5)) + (3 - R) * 8192 + U0 * 1024) : "memory");
}
__device__ __forceinline__ Ring ring_at(uint32_t sb, int k) {
    Ring r;
    r.n = 0;
    r.full = sb + OFF_BAR + B_FULL;
    asm("mapa.shared::cluster.u32 %0, %1, %2;" : "=r"(r.rel) : "r"(sb + OFF_BAR + B_EMPTY), "r"((threadIdx.x >> 5) & 1));
    r.sig = __shfl_sync(~0u, threadIdx.x & 95, threadIdx.x) == 0;
    return r;
}

template <bool BY_SM> __global__ void __cluster_dims__(2, 1, 1) __launch_bounds__(512, 1)
fused_kernel(const __grid_constant__ CUtensorMap tmX, const __grid_constant__ CUtensorMap tmBre, const __grid_constant__ CUtensorMap tmBim,
             const __grid_constant__ CUtensorMap tmCre, const __grid_constant__ CUtensorMap tmCim, const __grid_constant__ CUtensorMap tmXd,
             const __grid_constant__ CUtensorMap tmUst, const __grid_constant__ CUtensorMap tmVst,
             const __grid_constant__ CUtensorMap tmWr, const __grid_constant__ CUtensorMap tmWi, const __grid_constant__ CUtensorMap tmXa,
             const Params p) {
    extern __shared__ __align__(1024) uint8_t smraw[];
    asm volatile(".reg .pred pk, p0;");
    const int tid = threadIdx.x, rank = blockIdx.x & 1;
    const uint32_t wi = __shfl_sync(~0u, smem_u32(smraw) + (tid >> 5), 0), sb = wi & ~15u, bars = sb + OFF_BAR;
    const int wg = (wi >> 2) & 3, w = wi & 3, lane = tid & 31, g = lane >> 2, q = lane & 3;
    if (wg != 3) asm volatile("barrier.cluster.arrive.relaxed.aligned; barrier.cluster.wait.aligned;" ::: "memory");
    else asm volatile("prefetch.tensormap [%0];" ::"l"(w == 0 ? &tmX : w == 1 ? &tmBre : &tmBim) : "memory");
    int role;
    {
        uint32_t T = blockIdx.x;
        if (BY_SM) asm("mov.u32 %0, %%smid;" : "=r"(T));
        T >>= 1;
        const uint32_t a = ((T - 32) * 37) >> 8;
        asm("{.reg .pred p; setp.lt.u32 p, %1, 62; selp.u32 %0, 4, -58, p; add.u32 %0, %0, %1;\n"
            "setp.lt.u32 p, %1, 60; selp.u32 %0, %2, %0, p; setp.lt.u32 p, %1, 32; selp.u32 %0, %3, %0, p;}"
            : "=&r"(role) : "r"(T), "r"(8 * (T - 31 - 7 * a) + 4 + a), "r"(8 * (T & 7) + (T >> 3)));
        role = 2 * role + rank;
    }
    const bool spare = role >= 128;
    const int tc = ((role >> 3) & 14) + rank, cb = (role >> 1) & 7;
    const int fb = role >> 5, fcb = role & 31, fpos = pos_of(fcb);
    const int nu = role == 128 ? 1 : (fcb || !role ? 2 : 0);

    if (wg == 3) {
        if (elect_one()) {
            const uint32_t b = bars + w * 8;
            STAMP5(57);
            mbar_init(b, 1);
            if (w < 3 && !spare) {
                mbar_expect_tx(b, 32768);
                tma5d(sb + w * 32768 + 16384, &tmX, w * 64, 0, 0, 0, tc, b);
                if (w == 0) { tma4d(sb, &tmBre, 0, 0, 0, cb * 4, b); tma4d(sb + 8192, &tmBim, 0, 0, 0, cb * 4, b); }
                STAMP5(58);
            }
#pragma unroll
            for (int o = 32; o < B_EPOCH; o += 32) mbar_init(b + o, o < B_EMPTY ? 1 : (o < B_STG ? 2 : (o < B_P3M ? 4 : 8)));
            asm volatile("fence.mbarrier_init.release.cluster;" ::: "memory");
        }
        __syncwarp();
        STAMP5(59);
        asm volatile("barrier.cluster.arrive.relaxed.aligned;" ::: "memory");
    }
    if (opaque32(wg) == 3) {
        asm volatile("setmaxnreg.dec.sync.aligned.u32 24;");
        asm volatile("barrier.cluster.wait.aligned;" ::: "memory");
        if (w == 0) {
            if (!spare && elect_one()) {
                STAMP(56);
#pragma unroll 1
                for (int k = 1; k < NST; k++) {
                    if (k >= 3) mbar_expect_tx(bars + B_FULL + k * 8, 32768);
                    tma4d_mc(sb + k * 32768 + rank * 8192, rank ? &tmBim : &tmBre, k * 64, 0, 0, cb * 4, bars + B_FULL + k * 8);
                    if (k >= 3) tma5d(sb + k * 32768 + 16384, &tmX, k * 64, 0, 0, 0, tc, bars + B_FULL + k * 8);
                }
#define RING_WAIT "mbarrier.try_wait.parity.shared::cta.b64 p, [fb + 256], ph; @p bra GO;\n" \
                  "WAIT: mbarrier.try_wait.parity.shared::cta.b64 p, [fb + 256], ph; add.u32 n, n, 1; setp.gt.or.u32 p, n, 32768, p; @!p bra WAIT;\nGO:\n"
#define RING_NEXT "pmevent 1; add.u32 o, o, 8; setp.eq.u32 p, o, 40; selp.u32 o, 0, o, p; @p xor.b32 ph, ph, 1; add.u32 fb, %1, o; shl.b32 t, o, 12; add.u32 da, %0, t;\n"
                asm volatile("{.reg .b32 o, k, kk, c2, da, db, fb, ph, n, t; .reg .pred p;\n"
                             "mov.b32 o, 0; mov.b32 k, 320; mov.b32 kk, 320; mov.b32 c2, 0; mov.b32 ph, 0; mov.b32 n, 0; mov.b32 fb, %1; mov.b32 da, %0; mov.b32 db, %2;\n"
                             "LOOP:\n" RING_WAIT
                             "cp.async.bulk.tensor.5d.shared::cluster.global.mbarrier::complete_tx::bytes [da], [%3, {kk,0,0,0,%5}], [fb];\n"
                             "cp.async.bulk.tensor.4d.shared::cluster.global.mbarrier::complete_tx::bytes.multicast::cluster [db], [%4, {kk,0,c2,%6}], [fb], %7;\n"
                             "mbarrier.arrive.expect_tx.shared::cta.b64 _, [fb], 32768;\n" RING_NEXT
                             "add.u32 db, %2, t; add.u32 k, k, 64; and.b32 kk, k, 1023; shr.u32 c2, k, 9; and.b32 c2, c2, 2; setp.ne.u32 p, k, 2048; @p bra LOOP;}"
                             ::"r"(sb + 16384), "r"(bars + B_FULL), "r"(sb + rank * 8192), "l"(&tmX), "l"(rank ? &tmBim : &tmBre), "r"(tc), "r"(cb * 4), "h"((uint16_t)3) : "memory");
                asm volatile("{.reg .b32 o, k, kk, da, db, fb, hb, ph, n, t; .reg .b64 m, src; .reg .pred p;\n"
                             "mov.b32 o, 16; mov.b32 k, 0; mov.b32 kk, 0; mov.b32 ph, 1; mov.b32 n, 0; add.u32 fb, %1, 16; add.u32 hb, %1, 72; add.u32 da, %0, 65536; add.u32 db, %2, 65536;\n"
                             "mov.b64 m, %3; mov.b64 src, %5;\n"
                             "GROUP: add.u32 t, %8, k;\n"
                             "OWN: mbarrier.try_wait.parity.shared::cta.b64 p, [t], 0; add.u32 n, n, 1; setp.gt.or.u32 p, n, 32768, p; @!p bra OWN;\n"
                             "LOOP:\n" RING_WAIT
                             "cp.async.bulk.shared::cluster.global.mbarrier::complete_tx::bytes [da], [src], 16384, [hb];\n"
                             "cp.async.bulk.tensor.5d.shared::cluster.global.mbarrier::complete_tx::bytes.multicast::cluster [db], [m, {kk,0,0,0,%6}], [fb], %7;\n"
                             "mbarrier.expect_tx.shared::cta.b64 [fb], 16384; mbarrier.arrive.expect_tx.shared::cta.b64 _, [hb], 16384;\n" RING_NEXT
                             "add.u32 db, %2, t; add.u64 src, src, 16384; sub.u64 m, %4, m; add.u32 k, k, 1; shl.b32 kk, k, 5; and.b32 kk, kk, 0x7c0;\n"
                             "and.b32 t, k, 1; mad.lo.u32 hb, t, 8, fb; add.u32 hb, hb, o; add.u32 hb, hb, 40;\n"
                             "and.b32 t, k, 7; setp.ne.u32 p, t, 0; @p bra LOOP; setp.ne.u32 p, k, 32; @p bra GROUP;}"
                             ::"r"(sb), "r"(bars + B_FULL), "r"(sb + 16384 + rank * 8192), "l"(&tmCre), "l"((uint64_t)&tmCre + (uint64_t)&tmCim),
                               "l"(g_H + (size_t)tc * 32 * 16384), "r"(cb * 8 + rank * 4), "h"((uint16_t)3), "r"(bars + B_HOWN) : "memory");
            }
        } else if (opaque32(w) == 1) {
            const unsigned ep = ld_rlx(g_epoch + role * 8) + 1;
            __syncwarp();
            if (elect_one()) {
                asm volatile("st.relaxed.gpu.global.u32 [%0], %1;" ::"l"(g_epoch + role * 8), "r"(ep) : "memory");
                asm volatile("st.shared.u32 [%0], %1;" ::"r"(bars + B_EPOCH), "r"(ep) : "memory");
                mbar_arrive(bars + B_EP);
            }
            int slot;
            const int kap1 = unit_of(role, 1, slot);
            uint32_t lph = 0;
            if (!spare) mbar_wait(bars + B_STGU, 0);
            STAMP(21);
            const int c0 = fb * 2048 + fpos * 64;
            if (elect_one()) {
                if (!spare) {
#pragma unroll 1
                    for (int r = 4; r < 8; r++) bulk_st(g_X + r * (32 * 16384) + c0 * 2, sb + OFF_P + r * 4096, 128);
                    tma2d_st(&tmUst, c0, 0, sb + OFF_P);
                    bulk_commit();
                    tma2d_st(&tmUst, c0, 64, sb + OFF_P + 8192);
                    bulk_commit();
                    asm volatile("cp.async.bulk.wait_group.read 1;" ::: "memory");
                    red_hint(g_cnt);
                }
            }
            STAMP(40);
#pragma unroll 1
            for (int e = 0; e < 4; e++) {
                if (e >= 2) {
                    if (e == nu) {
                        mbar_wait(bars + B_WFREE, !spare);
                        load_w_rows(sb + OFF_WD, &tmWr, &tmWi, kap1, bars + B_WD);
                    }
                    if (e - 2 < nu) mbar_wait(bars + B_STG, e & 1);
                    STAMPO(23, e - 2);
                    if (e == nu && elect_one()) {
                        const int c = (role ? slot : 256) * 32;
                        tma2d_st(&tmVst, c, 0, sb + OFF_P);
                        tma2d_st(&tmVst, c + 4096, 0, sb + OFF_P + 8192);
                        bulk_commit();
                        if (role) { bulk_wait_read(); red_hint(g_cnt + 64); } else bulk_wait_all();
                    }
                    if (e == 3 && !spare && elect_one()) {
                        mbar_expect_tx(bars + B_FG, 8192);
                        bulk_ld(sb + OFF_F, (const uint8_t*)g_tab + TAB_G + fb * 8192, 8192, bars + B_FG);
                    }
                }
                const uint32_t tg = e < 2 ? lane * 128 + ((((lane >> 1) & 2) ^ (lane & 3)) << 4) + (lane >> 3) * 4 : lane * 64 + (lane & 8) * 4 + (lane & 2) * 8 + (lane & 4) * 2;
                if (spare) {
                    if (e == 1) {
                        wait_cnt(g_cnt, 128 * ep);
                        STAMP(42);
#pragma unroll 1
                        for (int n = 0; n < 4096; n++) {
                            if (elect_one()) {
                                mbar_expect_tx(bars + B_LD, 8 * 16384);
#pragma unroll 1
                                for (int r = 0; r < 8; r++) bulk_ld(sb + r * 16384, g_X + (size_t)r * (32 * 16384), 16384, bars + B_LD);
                            }
                            mbar_wait(bars + B_LD, n & 1);
                            bool ok = true;
#pragma unroll 1
                            for (int r = 0; r < 8; r++) ok &= tags_ok<4096>(sb + r * 16384 + tg, ep);
                            if (ok) break;
                        }
                        if (elect_one()) mbar_arrive(bars + B_RAW);
                    }
                } else {
                    const uint32_t dst = sb + OFF_P + (e & 1) * 16384;
#define X_ST1
#define X_ST2
#define X_RETRY
#define X_ARG
                    asm volatile("{.reg .b32 n, a, v0, v1, v2, v3; .reg .pred p, pe, pu;\n"
                                 "elect.sync _|pe, 0xffffffff; setp.lt.u32 pu, %10, 2; mov.b32 n, 0; pmevent 1;\n"
                                 "POLL: ld.relaxed.gpu.global.u32 v0, [%1]; setp.eq.u32 p, v0, %2; @p bra LOAD;\n"
                                 "nanosleep.u32 20; add.u32 n, n, 1; setp.lt.u32 p, n, 32768; @p bra POLL;\n"
                                 "LOAD:\n" X_ST1 "cp.async.bulk.wait_group.read 0;\n"
                                 "@pe cp.async.bulk.shared::cluster.global.mbarrier::complete_tx::bytes [%3], [%4], 16384, [%5]; @pe mbarrier.arrive.expect_tx.shared::cta.b64 _, [%5], 16384;\n"
                                 "mov.b32 a, 0;\n"
                                 "WAIT: mbarrier.try_wait.parity.shared::cta.b64 p, [%5], %0; @p bra CHECK; add.u32 n, n, 1; setp.lt.u32 p, n, 65536; @p bra WAIT;\n"
                                 "CHECK:\n" X_ST2 "@pu bra FOUR;\n"
                                 "ld.shared.u32 a, [%7]; ld.shared.u32 v0, [%6 + 2048]; ld.shared.u32 v1, [%6 + 6144]; ld.shared.u32 v2, [%6 + 10240]; ld.shared.u32 v3, [%6 + 14336];\n"
                                 "lop3.b32 a, a, v0, %8, 0x7e; lop3.b32 v1, v1, v2, %8, 0x7e; lop3.b32 a, a, v3, %8, 0xf6; or.b32 a, a, v1;\n"
                                 "FOUR: ld.shared.u32 v0, [%6]; ld.shared.u32 v1, [%6 + 4096]; ld.shared.u32 v2, [%6 + 8192]; ld.shared.u32 v3, [%6 + 12288];\n"
                                 "lop3.b32 a, a, v0, %8, 0xf6; lop3.b32 a, a, v1, %8, 0xf6; lop3.b32 v2, v2, v3, %8, 0x7e; lop3.b32 a, a, v2, 1, 0xa8;\n"
                                 "setp.eq.u32 p, a, 0; vote.sync.all.pred p, p, -1; @p bra OK;\n" X_RETRY
                                 "add.u32 n, n, 16; setp.ge.u32 p, n, 65536; @p bra OK; xor.b32 %0, %0, 1; bra LOAD;\n"
                                 "OK: @pe mbarrier.arrive.shared::cta.b64 _, [%9]; pmevent 1; xor.b32 %0, %0, 1;}"
                                 : "+r"(lph)
                                 : "l"(g_cnt + e * 32), "r"(128 * ep), "r"(dst), "l"(g_X + (size_t)(e < 2 ? role + e * 128 : 254 + (fb * 32 + fpos) * 2 + e) * 16384), "r"(bars + B_LD),
                                   "r"(dst + tg), "r"(dst + (e == 3 ? (lane & 1) * 8192 + 32 : 0)), "r"(ep), "r"(bars + B_IN + e * 8), "r"(e) X_ARG : "memory");
                }
                if (e == 0 && !spare && elect_one()) {
                    tma2d_st(&tmUst, c0, 128, sb + OFF_P + 16384);
                    tma2d_st(&tmUst, c0, 192, sb + OFF_P + 24576);
                    bulk_commit();
                    bulk_wait_read();
                    red_hint(g_cnt + 32);
                }
            }
            if (!spare) {
                mbar_wait(bars + B_HOWN + 8, 0);
#pragma unroll 1
                for (int r = 0; r < 4; r++) {
                    if (r == 3) mbar_wait(bars + B_P3M, 0);
                    if (elect_one()) {
                        if (r == 0) { mbar_expect_tx(bars + B_XD, 24576 + 256); mbar_expect_tx(bars + B_XD + 8, 8192); bulk_ld(sb + OFF_LAM, p.dsk + cb * 128, 256, bars + B_XD); }
                        tma4d(sb + OFF_F + (3 - r) * 8192, &tmXd, 0, tc * 128 + 32 * (r & 1) + 16 * (r >> 1), 0, cb * 2, bars + B_XD + (r == 3) * 8);
                    }
                    __nanosleep(PACE_X);
                }
            }
        } else {
            if (w == 2) {
                {
                    const int u = lane >> 4;
                    int slot;
                    const int r0 = unit_of(role, u, slot) + 512 * ((lane >> 1) & 3), r1 = (2048 - r0) & 2047, mir = (lane >> 3) & 1;
                    const unsigned short* wp = (const unsigned short*)((lane & 1) ? p.wi : p.wr);
                    const float a = bf2f(wp[r0 * 513 + mir * 512]), b = bf2f(wp[r1 * 513 + mir * 512]);
                    asm volatile("st.shared.f32 [%0], %1;" ::"r"(sb + OFF_WSP + u * 64 + (lane & 15) * 4), "f"(0.5f * ((lane & 1) ? (mir ? b - a : a - b) : a + b)) : "memory");
                }
                warp_arrive(bars + B_WSP);
                int slot;
                const int kap = unit_of(role, 0, slot);
                if (!spare) mbar_wait(bars + B_WFREE, 0);
                if (elect_one()) {
                    mbar_expect_tx(bars + B_FG, 8192);
                    bulk_ld(sb + OFF_F, (const uint8_t*)g_tab + TAB_FG, 8192, bars + B_FG);
                }
                if (nu) load_w_rows(sb + OFF_WD, &tmWr, &tmWi, kap, bars + B_WD);
            } else if (!spare) {
#pragma unroll 1
                for (int i = 0; i < 8; i++) {
                    if (i >= XA_N0) __nanosleep(XA_PACE);
                    if (elect_one()) {
                        const uint32_t xb = bars + (i < 4 ? B_RAW : B_XIN);
                        if (!(i & 3)) mbar_expect_tx(xb, 16384);
                        tma3d(sb + OFF_F + i * 4096, &tmXa, fcb * 32, 0, 4 * i + fb, xb);
                    }
                }
            }
            if (!spare) {
                const unsigned ep = get_epoch(bars);
#define CNT_RETRY
#define CNT_ARG
                asm volatile("{.reg .b32 o, k, hb, fb, ca, m, ph, rph, n, t, v0, v1, v2, v3; .reg .b64 src; .reg .pred p, pe;\n"
                             "elect.sync _|pe, 0xffffffff; mov.b32 o, %0; shr.u32 k, %0, 3; sub.u32 k, k, 2; mov.b32 m, 0x107c0; mov.b32 rph, 0; mov.b32 n, 0;\n"
                             "bra NEXT;\n"
                             "LOOP: mbarrier.try_wait.parity.shared::cta.b64 p, [hb], ph; @p bra GO;\n"
                             "WAIT: mbarrier.try_wait.parity.shared::cta.b64 p, [hb], ph; add.u32 n, n, 1; setp.gt.or.u32 p, n, 32768, p; @!p bra WAIT;\n"
                             "GO: ld.shared.u32 v0, [ca]; ld.shared.u32 v1, [ca + 128]; ld.shared.u32 v2, [ca + 256]; ld.shared.u32 v3, [ca + 384];\n"
                             "lop3.b32 v0, v0, v1, %4, 0x7e; lop3.b32 v2, v2, v3, %4, 0x7e; lop3.b32 v0, v0, v2, 1, 0xa8; setp.eq.u32 p, v0, 0; vote.sync.all.pred p, p, -1; @p bra OK;\n"
                             CNT_RETRY "add.u32 n, n, 16; setp.gt.u32 p, n, 32768; @p bra OK;\n"
                             "shl.b32 t, o, 12; add.u32 t, t, %5; mad.wide.u32 src, k, 16384, %6;\n"
                             "@pe mbarrier.arrive.expect_tx.shared::cta.b64 _, [%7], 16384; @pe cp.async.bulk.shared::cluster.global.mbarrier::complete_tx::bytes [t], [src], 16384, [%7];\n"
                             "AGAIN: mbarrier.try_wait.parity.shared::cta.b64 p, [%7], rph; add.u32 n, n, 1; setp.gt.or.u32 p, n, 32768, p; @!p bra AGAIN;\n"
                             "xor.b32 rph, rph, 1; bra GO;\n"
                             "OK: @pe mbarrier.arrive.shared::cta.b64 _, [fb]; pmevent 1;\n"
                             "add.u32 o, o, 16; setp.ge.u32 p, o, 40; @p sub.u32 o, o, 40; add.u32 k, k, 2;\n"
                             "NEXT: shr.u32 m, m, 1; and.b32 ph, m, 1; add.u32 fb, %1, o; mad.lo.u32 hb, o, 2, %2; mad.lo.u32 ca, o, 4096, %3; setp.lt.u32 p, k, 32; @p bra LOOP;}"
                             ::"r"(8 * w), "r"(bars + B_FULL), "r"(bars + B_HL - 16 + w * 8), "r"(sb + (q >> 1) * 8192 + (q & 1) * 512 + g * 1040 + q * 4), "r"(ep),
                               "r"(sb), "l"(g_H + (size_t)tc * 32 * 16384), "r"(bars + B_HR - 16 + w * 8) CNT_ARG : "memory");
                if (w == 3) warp_arrive(bars + B_DONE);
            }
        }
    } else {
        STAMP(55);
        asm volatile("setmaxnreg.inc.sync.aligned.u32 152;");
        STAMP5(60);
        const int t7 = tid & 127, hf = wg - 1;
        const int mi = lane >> 3, gl = lane & 7;
        if (spare && wg != 2) {
            if (tid < 64) { const uint4 v = __ldg((const uint4*)((const uint8_t*)g_tab + TAB_PC) + tid); sts128(sb + OFF_LAM + tid * 16, v.x, v.y, v.z, v.w); }
            bar_sync(1, 256);
            mbar_wait(bars + B_RAW, 0);
            STAMP(0);
#pragma unroll 1
            for (int u = 0; u < nu; u++) {
                int slot;
                const int t = unit_of(role, u, slot) >> 5;
                const uint32_t off = (tid >> 2) * 128 + q * 16;
                float zr[16], zi[16];
#pragma unroll
                for (int k = 0; k < 16; k++) zr[k] = zi[k] = 0.f;
#pragma unroll 1
                for (int r = (t & 1) ? 0 : t >> 1; r < 8 - ((t & 1) ? 0 : (t >> 1) - 1); r += (t & 1) ? 1 : 8 - t) {
                    float4 c;
                    float a[8], b[8];
                    lds128f(sb + OFF_LAM + t * 128 + r * 16, c.x, c.y, c.z, c.w);
                    lds128f(sb + r * 16384 + off, a[0], a[1], a[2], a[3]);
                    lds128f(sb + r * 16384 + off + 64, b[0], b[1], b[2], b[3]);
                    lds128f(sb + r * 16384 + off + 8192, a[4], a[5], a[6], a[7]);
                    lds128f(sb + r * 16384 + off + 8192 + 64, b[4], b[5], b[6], b[7]);
#pragma unroll
                    for (int k = 0; k < 16; k++) {
                        const uint32_t ua = __float_as_uint(a[k >> 1]), ub = __float_as_uint(b[k >> 1]);
                        const float x = __uint_as_float((k & 1) ? ua & 0xffff0000u : ua << 16), y = __uint_as_float((k & 1) ? ub & 0xffff0000u : ub << 16);
                        zr[k] = fmaf(c.x, x, fmaf(c.z, y, zr[k]));
                        zi[k] = fmaf(c.y, x, fmaf(c.w, y, zi[k]));
                    }
                }
                const uint32_t dst = sb + OFF_P + u * 16384 + off;
#pragma unroll
                for (int k = 0; k < 16; k += 8) {
                    sts128(dst + k * 1024, pk(zr[k], zr[k + 1]), pk(zr[k + 2], zr[k + 3]), pk(zr[k + 4], zr[k + 5]), pk(zr[k + 6], zr[k + 7]));
                    sts128(dst + k * 1024 + 64, pk(zi[k], zi[k + 1]), pk(zi[k + 2], zi[k + 3]), pk(zi[k + 4], zi[k + 5]), pk(zi[k + 6], zi[k + 7]));
                }
                fence_async_sm();
                bar_sync(1, 256);
                if (tid == 0) mbar_arrive(bars + B_IN + u * 8);
                STAMPO(1, u);
            }
            return;
        }
        if (wg == 2 && !spare) {
            asm volatile("setmaxnreg.inc.sync.aligned.u32 176;");
            uint32_t f1[16];
            cf tw[8];
            if (TAB_T0) __nanosleep(TAB_T0);
            ldtab<4, 2048>(f1, TAB_F1 + t7 * 16);
            ldtab_cf<16>(tw, TAB_TW1 + (t7 >> 2) * 64);
            const uint32_t ep = get_epoch(bars);
            uint32_t a0 = sb + OFF_P + (8 * w + gl + 32 * (mi >> 1)) * 128 + (((((mi & 1) << 2) | (fpos & 3)) ^ gl) << 4);
            float acc[128];
            const uint64_t dx = opaque(mkdesc(sb + OFF_F, 4096, 512, 2));
            mbar_wait(bars + B_RAW, 0);
            pinu(f1);
            wg_fence();
#pragma unroll
            for (int j = 0; j < 4; j++) mma128_rs<0, 1>(acc, f1[4 * j], f1[4 * j + 1], f1[4 * j + 2], f1[4 * j + 3], dx + j * 64, j);
            wg_commit();
            mbar_wait(bars + B_XIN, 0);
            wg_fence();
            STAMP(20);
#pragma unroll
            for (int j = 0; j < 4; j++) mma128_rs<64, 1>(acc, f1[4 * j], f1[4 * j + 1], f1[4 * j + 2], f1[4 * j + 3], dx + 1024 + j * 64, j);
            wg_commit();
            wg_wait<0>();
            pin(acc);
            pinu(f1);
            warp_arrive(bars + B_WFREE);
#pragma unroll 1
            for (int h = 0;; h++) {
                const uint32_t tmask = 2 * q + h == fpos >> 2 ? ~1u : ~0u, tbit = ep & ~tmask;
#pragma unroll
                for (int cl = 0; cl < 2; cl++) {
                    c2 v[8];
#pragma unroll
                    for (int n = 0; n < 8; n++) {
                        const int i = 4 * (4 * n + cl);
                        v[n] = {{acc[i], acc[i + 2]}, {acc[i + 1], acc[i + 3]}};
                    }
                    dft8<true, YP1>(v, tw);
#pragma unroll
                    for (int r = 0; r < 8; r += 2) {
                        uint32_t o0 = pk(v[r].a.x, v[r].b.x), o1 = pk(v[r].a.y, v[r].b.y), o2 = pk(v[r + 1].a.x, v[r + 1].b.x), o3 = pk(v[r + 1].a.y, v[r + 1].b.y);
                        if (cl == 0) { o0 = (o0 & tmask) | tbit; o2 = (o2 & tmask) | tbit; }
                        stsm4((a0 ^ (cl << 4)) + r * 4096, o0, o1, o2, o3);
                    }
                }
                if (h) break;
                a0 ^= 32;
#pragma unroll
                for (int n = 0; n < 8; n++) {
                    asm volatile("mov.b32 %0, %8; mov.b32 %1, %9; mov.b32 %2, %10; mov.b32 %3, %11; mov.b32 %4, %12; mov.b32 %5, %13; mov.b32 %6, %14; mov.b32 %7, %15; pmevent 1;"
                                 : "=&f"(acc[16 * n]), "=&f"(acc[16 * n + 1]), "=&f"(acc[16 * n + 2]), "=&f"(acc[16 * n + 3]), "=&f"(acc[16 * n + 4]), "=&f"(acc[16 * n + 5]), "=&f"(acc[16 * n + 6]), "=&f"(acc[16 * n + 7])
                                 : "f"(acc[16 * n + 8]), "f"(acc[16 * n + 9]), "f"(acc[16 * n + 10]), "f"(acc[16 * n + 11]), "f"(acc[16 * n + 12]), "f"(acc[16 * n + 13]), "f"(acc[16 * n + 14]), "f"(acc[16 * n + 15]));
                }
            }
            fence_async_sm();
            warp_arrive(bars + B_STGU);
            bar_sync(3, 128);
            asm volatile("setmaxnreg.dec.sync.aligned.u32 152;");
            bar_arrive(7, 256);
        }
        if (wg == 1) {
            if (LAM_T0) __nanosleep(LAM_T0);
            const int cl = tid & 127, ch = (cl >> 6) * 512 + ((cl >> 3) & 1) * 256 + cb * 32 + ((cl >> 4) & 3) * 8 + (cl & 7);
            const float lr = bf2f(*(const unsigned short*)padd(p.lre, 2 * ch)), li = bf2f(*(const unsigned short*)padd(p.lim, 2 * ch));
            const float dt = __bfloat162float(__float2bfloat16(expf(bf2f(*(const unsigned short*)padd(p.ldt, 2 * ch)))));
            const float an = dt * li, th = an * 0.318309873342514f;
            float sn, cs, inv;
            sincospif(fmaf(rintf(0.5f * th), -2.f, th) + fmaf(an, 1.2841276653e-8f, fmaf(an, 0.318309873342514f, -th)), &sn, &cs);
            const float ex = expf(dt * lr), br = ex * cs, bi = ex * sn;
            asm("rcp.approx.f32 %0, %1;" : "=f"(inv) : "f"(lr * lr + li * li));
            inv += inv;
            const float cr = ((br - 1.f) * lr + bi * li) * inv, ci = (bi * lr - (br - 1.f) * li) * inv;
            sts128(sb + OFF_LAM + cl * 16, __float_as_uint(br), __float_as_uint(-bi), __float_as_uint(cr), __float_as_uint(-ci));
            mbar_wait(bars + B_EP, 0);
            bar_sync(8, 128);
            if (tid == 128) mbar_arrive(bars + B_LAM);
        }
        if (wg != 2) {
        if (wg == 0) bar_sync(4, 128); else bar_sync(7, 256);
        asm volatile("setmaxnreg.inc.sync.aligned.u32 160;");
        if (wg == 0) bar_sync(4, 128);
        float d[128];
        STAMPW(0, 10);
        Ring rg = ring_at(sb, role * 66 + wg * 16);
        cf lam[2];
        unsigned ep;
        gemm1(d, rg, ring_desc(sb, 0, 16, 1), ring_desc(sb, 16384, 16, 1), wg);
        const uint32_t lama = sb + OFF_LAM + wg * 1024 + w * 256 + (fresh_lane() & 28) * 4;
        mbar_wait_fast(bars + B_LAM, 0);
        lam[0] = lds_cf(lama); lam[1] = lds_cf(lama + 128);
        asm volatile("ld.shared.u32 %0, [%1];" : "=r"(ep) : "r"(bars + B_EPOCH) : "memory");
        asm volatile("setmaxnreg.inc.sync.aligned.u32 176;");
        cf L[2] = {lam[0], lam[1]};
#pragma unroll
        for (int i = 0; i < 4; i++) { L[0] = csq(L[0]); L[1] = csq(L[1]); }
        asm volatile("" : "+f"(L[0].x), "+f"(L[0].y), "+f"(L[1].x), "+f"(L[1].y)::"memory");
        wg_wait<0>();
        ring_release(rg, 8 * wg);
        pin(d);
        STAMPW(1, 11);
        {
            const int lane = fresh_lane(), g = lane >> 2, q = lane & 3, mi = lane >> 3, gl = lane & 7;
            cf f[2], fb2[2];
#pragma unroll
            for (int i = 0; i < 17; i++) {
#pragma unroll
                for (int h = 0; h < 2; h++) {
                    const int r = 4 * (i >> 1) + 2 * h + (i & 1), r2 = 32 + 4 * ((i - 1) >> 1) + 2 * h + ((i - 1) & 1);
                    if (i < 16) f[h] = i ? cfma(lam[h], f[h], {d[r], -d[64 + r]}) : cf{d[r], -d[64 + r]};
                    if (i > 0) fb2[h] = i > 1 ? cfma(lam[h], fb2[h], {d[r2], -d[64 + r2]}) : cf{d[r2], -d[64 + r2]};
                    if (i && (h || !(YS & 8))) YIELD_S1();
                }
            }
            const uint8_t* cbase = (const uint8_t*)g_carry + (tc * 16 + wg * 8 + cb) * 512 + w * 64;
            const uint8_t* cptr = padd(cbase, g * 8);
            const unsigned tag = ep & 15u;
#pragma unroll
            for (int h = 0; h < 2; h++) { f[h] = cfma(L[h], f[h], fb2[h]); L[h] = csq(L[h]); }
            cf s0[2], s1[2], s2[2];
#pragma unroll
            for (int h = 0; h < 2; h++) {
                s0[h] = {__shfl_sync(~0u, f[h].x, 0, 4), __shfl_sync(~0u, f[h].y, 0, 4)};
                s1[h] = {__shfl_sync(~0u, f[h].x, 1, 4), __shfl_sync(~0u, f[h].y, 1, 4)};
                s2[h] = {__shfl_sync(~0u, f[h].x, 2, 4), __shfl_sync(~0u, f[h].y, 2, 4)};
            }
#pragma unroll
            for (int h = 0; h < 2; h++) {
                s1[h] = cfma(L[h], s0[h], s1[h]);
                s2[h] = cfma(L[h], s1[h], s2[h]);
                f[h] = cfma(L[h], s2[h], f[h]);
                asm volatile("{.reg .pred p; .reg .b64 a; setp.eq.u32 p, %3, 3; mov.b64 a, {%1,%2}; @p st.relaxed.gpu.global.b64 [%0], a;}" ::"l"(cptr + h * 256),
                             "r"((__float_as_uint(f[h].x) & ~15u) | tag), "f"(f[h].y), "r"(q) : "memory");
            }
            STAMPX(2, 12);
            cf gam = lds_cf(lama + 8);
            cf st = csel(q & 2, csel(q & 1, s2[0], s1[0]), csel(q & 1, s0[0], {0.f, 0.f}));
            const cf st1 = csel(q & 2, csel(q & 1, s2[1], s1[1]), csel(q & 1, s0[1], {0.f, 0.f}));
            cptr = padd(cbase - 4 * 8192, (3 - mi) * 8192 + gl * 8);
            const int nprev = tc - 1 - mi;
            const uint8_t* hptr = padd(g_H + (size_t)(tc * 32 + wg * 16 + (cb & 6)) * 16384 + ((cb & 1) * 4 + w) * 1024, g * 64 + ((q ^ (g >> 1)) << 4));
            const uint32_t hm = 4 * (g & 1) + (q ^ (g >> 1)) == (cb & 1) * 4 + w ? ~1u : ~0u;
            float u[64];
            uint64_t fv[4] = {tag, tag, tag, tag};
            prescale<0>(u, d, gam);
            gather(fv, cptr, nprev);
#pragma unroll 1
            for (int h = 0;; h++) {
                const cf L2 = csq(L[0]), M = csq(L2);
                cf M4 = csq(csq(M));
                M4 = {__shfl_sync(~0u, M4.x, 4 * gl), __shfl_sync(~0u, M4.y, 4 * gl)};
                cf lq = cmul(gam, cmul(csel(q & 1, L[0], {1.f, 0.f}), csel(q & 2, L2, {1.f, 0.f})));
                st = cmul(gam, st);
                asm volatile("pmevent 1;" : "+f"(lq.x), "+f"(lq.y), "+f"(st.x), "+f"(st.y));
#pragma unroll 1
                for (unsigned n = 0; __any_sync(~0u, (((uint32_t)fv[0] ^ tag) | ((uint32_t)fv[1] ^ tag) | ((uint32_t)fv[2] ^ tag) | ((uint32_t)fv[3] ^ tag)) & 15u) && n < SPIN_LIMIT; n++) gather(fv, cptr, nprev);
                if (!h) STAMPX(53, 54);
                cf P = as_cf(fv[3]), pj[4];
#pragma unroll
                for (int a = 2; a >= 0; a--) P = cfma(M4, P, as_cf(fv[a]));
                cptr += 256;
                asm volatile("" : "+f"(P.x), "+f"(P.y)::"memory");
                gather(fv, cptr, h ? -1 : nprev);
#pragma unroll
                for (int j = 3; j >= 0; j--) pj[j] = {__shfl_sync(~0u, P.x, g + 8 * j), __shfl_sync(~0u, P.y, g + 8 * j)};
                st = cfma(lq, cfma(M, cfma(M, cfma(M, pj[3], pj[2]), pj[1]), pj[0]), st);
                if (!h) STAMPX(3, 13);
                uint32_t keep = sb >> 28;
                scan2(u, lam[0], st, hptr, hm, ep & ~hm, keep);
                warp_arrive(bars + B_HOWN + wg * 16 + h * 8 + keep);
                if (h) break;
                STAMPW(4, 14);
                if (wg == 1 && nu) bar_sync(9, 256);
                lds128f(lama + 128, lam[0].x, lam[0].y, gam.x, gam.y);
                st = st1;
                L[0] = L[1];
                hptr += 8 * 16384;
                prescale<1>(u, d, gam);
            }
            STAMPW(5, 15);
        }
        if (wg == 0) bar_sync(4, 128); else bar_sync(8, 128);
        if (wg == 0) {
            asm volatile("setmaxnreg.dec.sync.aligned.u32 160;");
            float y[128];
            rg = ring_at(sb, role * 66 + 32);
            STAMP(6);
            STAMP(7);
            const uint64_t dA = ring_desc(sb, 0, 512, 2), dB = ring_desc(sb, 16384, 16, 1);
            gemm2(y, rg, dA, dB, 0);
            asm volatile("setmaxnreg.inc.sync.aligned.u32 184;");
            const int lane = fresh_lane(), g = lane >> 2, q = lane & 3;
            const int pg = 2 * (g & 3) + (g >> 2);
            float* op = (float*)padd(p.out + (size_t)(tc * 128 + 64 * (w & 1) + 8 * (w >> 1)) * 2048 + 1024 + cb * 128, pg * 8192 + q * 16);
            const uint32_t xa = sb + OFF_F + (16 * (w & 1) + 8 * (w >> 1) + pg) * 128 + (((q >> 1) ^ pg) << 4) + (q & 1) * 8;
#define HALF0(k) wg_fence(); peek(k < 63 ? rg.full + SL(k + 1) * 8 : bars + B_XD, PH(k + 1)); half_step<0, k>(y, dA, dB); wg_commit(); peek_wait(k < 63 ? rg.full + SL(k + 1) * 8 : bars + B_XD, PH(k + 1), rg.n);
            HALF0(60) HALF0(61) HALF0(62) HALF0(63)
            const uint64_t dB2 = ring_desc(sb >> 1, 16384, 16, 1);
            uint32_t xa0[8], xa1[8], dd[16];
#pragma unroll
            for (int i = 0; i < 8; i++) asm volatile("ld.shared.v2.b32 {%0,%1}, [%2];" : "=r"(dd[2 * i]), "=r"(dd[2 * i + 1]) : "r"(sb + OFF_LAM + q * 8 + 32 * i) : "memory");
            load_x4<0, 0>(xa0, xa);
            wg_fence();
            half_step<64, 64 - SKEW>(y, dA, dB2);
            wg_commit();
            wg_wait<1>();
#pragma unroll
            for (int i = 0; i < 64; i++) asm volatile("" : "+f"(y[i])::"memory");
            STAMP(16);
#define MM(n) if (4 + (n) < 4 * SKEW) { wg_fence(); mma_h<64, 65 - SKEW + (n) / 4, (n) % 4>(y, dA, dB2); mma_h<64, 65 - SKEW + (n) / 4, (n) % 4 + 1>(y, dA, dB2); }
#define OUT4(R, U, X, n) out_piece<R, U>(y, dd, X[0], X[1], op); MM(n) out_piece<R, U + 1>(y, dd, X[2], X[3], op); MM(n + 2) \
                         out_piece<R, U + 2>(y, dd, X[4], X[5], op); MM(n + 4) out_piece<R, U + 3>(y, dd, X[6], X[7], op); MM(n + 6)
            load_x4<0, 4>(xa1, xa);
            OUT4(0, 0, xa0, 0)
            load_x4<1, 0>(xa0, xa);
            OUT4(0, 4, xa1, 8)
            wg_commit();
            load_x4<1, 4>(xa1, xa);
            OUT4(1, 0, xa0, 16)
            load_x4<2, 0>(xa0, xa);
            OUT4(1, 4, xa1, 16)
            STAMP(18);
            wg_wait<0>();
#pragma unroll
            for (int i = 64; i < 128; i++) asm volatile("" : "+f"(y[i])::"memory");
            STAMP(8);
            load_x4<2, 4>(xa1, xa);
            mbar_wait_fast(bars + B_XD + 8, 0);
            OUT4(2, 0, xa0, 16)
            load_x4<3, 0>(xa0, xa);
            OUT4(2, 4, xa1, 16)
            load_x4<3, 4>(xa1, xa);
            OUT4(3, 0, xa0, 16)
            OUT4(3, 4, xa1, 16)
            STAMP(9);
            return;
        }
        asm volatile("setmaxnreg.dec.sync.aligned.u32 152;");
        } else {
        if (nu) {
            cf T[8];
            const uint32_t ep = get_epoch(bars);
            const int ka = pos_of(t7 >> 2);
            {
                const cf s8 = twid(8 * ka, 1024);
                T[0] = twid(2 * q * ka, 1024);
                T[1] = twid((2 * q + 1) * ka, 1024);
#pragma unroll
                for (int i = 2; i < 8; i++) T[i] = cmul(T[i - 2], s8);
#pragma unroll
                for (int i = 0; i < 8; i += 2) asm volatile("pmevent 1;" : "+f"(T[i].x), "+f"(T[i].y), "+f"(T[i + 1].x), "+f"(T[i + 1].y));
            }
            asm volatile("setp.eq.u32 p0, %0, 0;" ::"r"(__shfl_sync(~0u, t7, lane)));
            mbar_wait(bars + B_WSP, 0);
            mbar_wait(bars + B_FG, 0);
            uint32_t wd[4], wm[4], vo[32];
            const uint8_t* vp;
            int slot;
            const int kap0 = unit_of(role, 0, slot), al = 2 * kap0;
            const int kap1 = __shfl_sync(~0u, unit_of(role, 1, slot), 0);
            slot = __shfl_sync(~0u, slot, 0);
            cf be1 = twid(kap0 + 512 * q, 2048), be2 = csq(be1), be3 = cmul(be1, be2);
#pragma unroll
            for (int j = 0; j < 4; j++) {
                wd[j] = sb + OFF_WD + ((j + q) & 3) * WPITCH + (al & 15) + 2 * ka + 64 * q;
                wm[j] = sb + OFF_WM + (((role ? 3 : 4) - j - q) & 3) * WPITCH + (-al & 15) + 1024 - 2 * ka - 64 * q;
                wd[j] = __shfl_sync(~0u, wd[j], lane);
            }
#pragma unroll 1
            for (int u = 0; u < nu; u++) {
                const uint32_t buf = sb + OFF_P + u * 16384;
                float acc[64], za[32], zb[32], ya[32], yb[32], vv[64];
                const uint64_t dF = opaque(mkdesc(sb + OFF_F, 16, 1024, 1)), dB = opaque(mkdesc(buf, 4096, 512, 2));
                mbar_wait(bars + B_IN + u * 8, 0);
                if (!role) {
                    const uint32_t z = buf + w * 1024 + (fresh_lane() >> 2) * 128 + 64 + (fresh_lane() & 3) * 16;
#pragma unroll
                    for (int i = 0; i < 4; i++) sts128(z + i * 4096, 0, 0, 0, 0);
                    fence_async_sm();
                    bar_sync(3, 128);
                }
                STAMP3(22);
                wg_fence();
#pragma unroll
                for (int j = 0; j < 4; j++) mma128_ss<0, 0, 1>(acc, dF + j * 2, dB + j * 64, j);
                wg_commit();
                if (u) {
                    const uint32_t va = sb + OFF_P + (((uint32_t)(uintptr_t)vp - (uint32_t)(uintptr_t)g_X) >> 9 & 0x7c0) + ((uint32_t)(uintptr_t)vp & 31) + (fresh_lane() & 4) * 8;
                    bar_sync(3, 128);
#pragma unroll
                    for (int k = 0; k < 16; k++) sts64(va + ((k >> 1) & 1) * 8192 + (k >> 2) * 2048 + (k & 1) * 256, vo[2 * k], vo[2 * k + 1]);
                    fence_async_sm();
                    warp_arrive(bars + B_STG);
                    if (!role) { const uint32_t t = wm[0]; wm[0] = wm[1]; wm[1] = wm[2]; wm[2] = wm[3]; wm[3] = t; }
                }
                STAMP3(39);
                wg_wait<0>();
                pin(acc);
                STAMP3(30);
                uint32_t af[16], ag[16];
#pragma unroll
                for (int k = 0; k < 8; k++) {
                    uint32_t(&o)[16] = k < 4 ? af : ag;
                    const int c = k & 3;
#pragma unroll
                    for (int b = 0; b < 2; b++) {
                        const int i = 4 * (4 * ((k >> 2) * 2 + b) + c);
                        c2 x = mul2(c2{{acc[i], acc[i + 2]}, {acc[i + 1], acc[i + 3]}}, c2{T[2 * c], T[2 * c + 1]});
                        o[4 * c + b] = pk(x.a.x, x.a.y);
                        o[4 * c + 2 + b] = pk(x.b.x, x.b.y);
                    }
                    asm volatile("" : "+r"(o[4 * c]), "+r"(o[4 * c + 1]), "+r"(o[4 * c + 2]), "+r"(o[4 * c + 3])::"memory");
                    wg_fence();
                    mma64_rs<0>(k < 4 ? za : zb, o[4 * c], o[4 * c + 1], o[4 * c + 2], o[4 * c + 3], dF + c * 2, c);
                }
                wg_commit();
                STAMP3(31);
                mbar_wait_fast(bars + B_WD, u & 1);
                STAMP3(37);
                uint32_t wr[16];
#pragma unroll
                for (int i = 0; i < 16; i++) wr[i] = lds16(wd[i >> 2] + 256 * ((i >> 1) & 1) + (i & 1) * 4 * WPITCH);
                wg_wait<0>();
                pin(za);
                pin(zb);
                pinu(af);
                pinu(ag);
                STAMP3(32);
#pragma unroll
                for (int jb = 0; jb < 4; jb++) {
                    const int i = 8 * jb;
                    c2 s0 = {{za[i], za[i + 4]}, {za[i + 1], za[i + 5]}}, s2 = {{za[i + 2], za[i + 6]}, {za[i + 3], za[i + 7]}};
                    c2 s1 = {{zb[i], zb[i + 4]}, {zb[i + 1], zb[i + 5]}}, s3 = {{zb[i + 2], zb[i + 6]}, {zb[i + 3], zb[i + 7]}};
                    c2 W[4];
                    auto wcvt = [&](int j) {
                        asm volatile("shl.b32 %0, %4, 16; shl.b32 %1, %5, 16; shl.b32 %2, %6, 16; shl.b32 %3, %7, 16;"
                                     : "=&f"(W[j].a.x), "=&f"(W[j].a.y), "=&f"(W[j].b.x), "=&f"(W[j].b.y) : "r"(wr[4 * j]), "r"(wr[4 * j + 1]), "r"(wr[4 * j + 2]), "r"(wr[4 * j + 3]));
                        if ((jb & 1) == 0)
                            asm volatile("@p0 ld.shared.v2.f32 {%0,%1}, [%2];" : "+f"(W[j].a.x), "+f"(W[j].a.y) : "r"(sb + OFF_WSP + u * 64 + jb * 16 + j * 8));
                        if (jb < 3) {
#pragma unroll
                            for (int k = 4 * j; k < 4 * j + 4; k++) {
                                const int e = (k >> 1) & 1, pl = (k & 1) * 4 * WPITCH;
                                wr[k] = jb == 0 ? lds16(wd[j] + 512 + 256 * e + pl) : lds16(wm[j] - 512 * (jb - 1) - 256 * e + pl);
                            }
                        }
                        if (jb >= 2) { W[j].a.y = -W[j].a.y; W[j].b.y = -W[j].b.y; }
                    };
                    wcvt(0);
                    s2 = mul2(s2, be1);
                    s1 = fma2(s1, be2, s0);
                    wcvt(1);
                    s3 = fma2(s3, be3, s2);
                    { const c2 x = twm2(s0, s1), y = twm2(s2, s3); s0 = s1; s2 = s3; s1 = x; s3 = y; }
                    wcvt(2);
                    bfly<0>(s0, s2); bfly_mi<0>(s1, s3);
                    wcvt(3);
                    s0 = mul2(s0, W[0]); s1 = mul2(s1, W[1]);
                    bfly_tw<0>(s0, s2, W[2], s1, s3, W[3]);
                    bfly<0>(s0, s1); bfly_mi<0>(s2, s3);
                    af[4 * jb] = pk(s0.a.x, s0.b.x); af[4 * jb + 1] = pk(s3.a.x, s3.b.x); af[4 * jb + 2] = pk(s0.a.y, s0.b.y); af[4 * jb + 3] = pk(s3.a.y, s3.b.y);
                    ag[4 * jb] = pk(s1.a.x, s1.b.x); ag[4 * jb + 1] = pk(s2.a.x, s2.b.x); ag[4 * jb + 2] = pk(s1.a.y, s1.b.y); ag[4 * jb + 3] = pk(s2.a.y, s2.b.y);
                }
                pinu(af);
                pinu(ag);
                warp_arrive(bars + B_WFREE);
                wg_fence();
#pragma unroll
                for (int j = 0; j < 4; j++) mma64_rs<1>(ya, af[4 * j], af[4 * j + 1], af[4 * j + 2], af[4 * j + 3], dF + j * 128, j);
                wg_commit();
#pragma unroll
                for (int j = 0; j < 4; j++) mma64_rs<1>(yb, ag[4 * j], ag[4 * j + 1], ag[4 * j + 2], ag[4 * j + 3], dF + j * 128, j);
                wg_commit();
                STAMP3(33);
                {
                    const uint32_t a0 = buf + (mi & 1) * 4096 + (16 * w + 8 * (mi >> 1) + gl) * 64 + ((gl >> 1) << 4);
#pragma unroll
                    for (int h = 0; h < 2; h++) {
                        if (h == 0) { wg_wait<1>(); pin(ya); pinu(af); STAMP3(34); } else { wg_wait<0>(); pin(yb); pinu(ag); }
                        const float(&yy)[32] = h ? yb : ya;
#pragma unroll
                        for (int c = 0; c < 4; c++) {
                            const int i = 8 * ((c + 2 * h) & 3), k = 8 * ((c + 2 * h + 1) & 3) + 2;
                            c2 x = {cmulc({yy[i], yy[i + 1]}, T[2 * c]), cmulc({yy[k], yy[k + 1]}, T[2 * c])};
                            fin<1>(x);
                            c2 y = {cmulc({yy[i + 4], yy[i + 5]}, T[2 * c + 1]), cmulc({yy[k + 4], yy[k + 5]}, T[2 * c + 1])};
                            fin<1>(y);
                            stsm4((a0 ^ (c << 4)) + h * 8192, pk(x.a.x, y.a.x), pk(x.b.x, y.b.x), pk(x.a.y, y.a.y), pk(x.b.y, y.b.y));
                        }
                    }
                }
                STAMP3(38);
                fence_async_sm();
                bar_sync(3, 128);
                wg_fence();
#pragma unroll
                for (int j = 0; j < 4; j++) mma128_ss<0, 1, 1>(vv, dF + j * 128, dB + j * 64, j);
                wg_commit();
                STAMP3(35);
                const int lane = fresh_lane(), g = lane >> 2, q = lane & 3;
                vp = padd(g_X + (4 << 20) + w * (8 * 32768) + (role ? u : 1) * 16384 + slot * 64,
                                         (g >> 1) * 32768 + (role ? g & 1 : u) * 32 + (((q ^ (slot >> 1)) & 1) << 4) + (q >> 1) * 8);
                const uint32_t tmask = (((g & 1) == ((slot >> 3) & 1) || !role) && q == ((slot >> 1) & 2)) ? ~1u : ~0u, tbit = (ep ^ (role + u ? 0 : g)) & ~tmask;
                be1 = twid(kap1 + 512 * q, 2048); be2 = csq(be1); be3 = cmul(be1, be2);
                asm volatile("pmevent 1;" : "+f"(be1.x), "+f"(be1.y), "+f"(be2.x), "+f"(be2.y), "+f"(be3.x), "+f"(be3.y), "+l"(vp)::"memory");
                wg_wait<0>();
                pin(vv);
                STAMP3(36);
#pragma unroll
                for (int k = 0; k < 16; k++) {
                    const int i = 8 * (k >> 1) + 2 * (k & 1);
                    vo[2 * k] = (pk(vv[i], vv[i + 1]) & tmask) | tbit;
                    vo[2 * k + 1] = pk(vv[i + 4], vv[i + 5]);
                }
                pinu(vo);
            }
            if (!role) mbar_wait(bars + B_IN + 16, 0);
            warp_arrive(bars + B_STG);
            const bool odd = fresh_lane() & 4;
            store_v<0, 4>(vo, vp, role || !odd);
            asm volatile("@p0 red.relaxed.gpu.global.add.u32 [%0], 1;" ::"l"(g_cnt + 32 + nu * 32) : "memory");
            store_v<4, 16>(vo, vp, role || odd);
            if (!spare) bar_arrive(9, 256);
        }
        if (spare) return;
        }
        {
            constexpr int Y = YP3;
            uint32_t sp[8];
            cf tw[8];
            if (hf) __nanosleep(400);
            ldtab<2, 2048>(sp, TAB_SP + fb * 4096 + t7 * 16);
            ldtab_cf<16>(tw, TAB_TW3 + fb * 2048 + (t7 >> 2) * 64);
            const uint64_t dF = opaque(mkdesc(sb + OFF_F, 16, 1024, 1)), dB = opaque(mkdesc(sb + OFF_P + hf * 8192, 1024, 256, 3));
            const uint8_t* op = padd(p.out + (1024 + fb) * 2048 + fcb * 32 + hf * 16, (t7 >> 2) * 32768 + (q >> 1) * 16 + (q & 1) * 32);
            float acc[64], out[64];
            mbar_wait(bars + B_IN + 24, 0);
            mbar_wait(bars + B_FG, 1);
            STAMP(25);
            pinu(sp);
            wg_fence();
#pragma unroll
            for (int j = 0; j < 4; j++) {
                const uint64_t db = dB + (j >> 1) * 1024 + (j & 1) * 32;
                mma112_ss(acc, dF + j * 2, db + 64, j);
                if (j & 1) mma16_rs(acc, 0u, sp[2 * j], 0u, sp[2 * j + 1], db, 1);
                else mma16_rs(acc, sp[2 * j], 0u, sp[2 * j + 1], 0u, db, j);
            }
            wg_commit();
            wg_wait<0>();
            pin(acc);
            pinu(sp);
            warp_arrive(bars + B_P3M);
            if (!hf) bar_sync(5, 256);
#pragma unroll
            for (int cl = 0; cl < 2; cl++) {
                c2 z[8];
#pragma unroll
                for (int n = 0; n < 8; n++) {
                    const int i = 4 * (2 * n + cl);
                    z[n] = {{acc[i], acc[i + 2]}, {acc[i + 1], acc[i + 3]}};
                }
                z[0] = {{z[0].a.x + z[0].a.y, z[0].a.x - z[0].a.y}, {z[0].b.x + z[0].b.y, z[0].b.x - z[0].b.y}};
                z[4] = mul2(z[4], tw[4]);
                fin<Y>(z[0], z[4]);
#pragma unroll
                for (int n = 1; n < 4; n++) {
                    const cf iw = n == 1 ? cf{0.38268343236508977f, 0.92387953251128674f}
                                         : (n == 2 ? cf{0.70710678118654752f, 0.70710678118654752f} : cf{0.92387953251128674f, 0.38268343236508977f});
                    c2 y = mul2(z[n], tw[n]);
                    fin<Y>(y);
                    const cf t = {tw[8 - n].x, -tw[8 - n].y};
                    c2 E = fma2(c2{{z[8 - n].a.x, -z[8 - n].a.y}, {z[8 - n].b.x, -z[8 - n].b.y}}, t, y);
                    fin<Y>(E);
                    z[n] = fma2(twm2(y, E), iw, E);
                    fin<Y>(z[n]);
                    z[8 - n] = {{fmaf(2.f, E.a.x, -z[n].a.x), fmaf(-2.f, E.a.y, z[n].a.y)}, {fmaf(2.f, E.b.x, -z[n].b.x), fmaf(-2.f, E.b.y, z[n].b.y)}};
                }
                dft8<false, Y>(z, tw);
#pragma unroll
                for (int m = 0; m < 8; m++) {
                    out[8 * m + 2 * cl] = z[m].a.x; out[8 * m + 2 * cl + 1] = z[m].b.x;
                    out[8 * m + 4 + 2 * cl] = z[m].a.y; out[8 * m + 5 + 2 * cl] = z[m].b.y;
                }
            }
            pin(out);
            if (hf) bar_arrive(5, 256);
            if (hf) STAMP(26);
#pragma unroll
            for (int m = 0; m < 16; m++) {
                asm volatile("st.global.v4.f32 [%0], {%1,%2,%3,%4};" ::"l"(op + (m - 8) * (1 << 20)), "f"(out[4 * m]), "f"(out[4 * m + 1]), "f"(out[4 * m + 2]), "f"(out[4 * m + 3]) : "memory");
                if (PACE_O && m < 15 && m % PACE_ON == PACE_ON - 1)
                    asm volatile("{.reg .pred p; mbarrier.test_wait.parity.shared::cta.b64 p, [%0], 0; @!p nanosleep.u32 %1;}" ::"r"(bars + B_DONE), "n"(PACE_O) : "memory");
            }
            STAMP(27);
        }
    }
}

typedef CUresult (*EncodeFn)(CUtensorMap*, CUtensorMapDataType, cuuint32_t, void*, const cuuint64_t*, const cuuint64_t*, const cuuint32_t*,
                             const cuuint32_t*, CUtensorMapInterleave, CUtensorMapSwizzle, CUtensorMapL2promotion, CUtensorMapFloatOOBfill);

static CUtensorMap make_map(EncodeFn enc, const void* ptr, int rank, const cuuint64_t* dims, const cuuint64_t* strides, const cuuint32_t* box,
                            CUtensorMapSwizzle swz, CUtensorMapL2promotion promo, CUtensorMapDataType dt = CU_TENSOR_MAP_DATA_TYPE_BFLOAT16) {
    CUtensorMap m;
    const cuuint32_t es[5] = {1, 1, 1, 1, 1};
    enc(&m, dt, rank, const_cast<void*>(ptr), dims, strides, box, es, CU_TENSOR_MAP_INTERLEAVE_NONE, swz, promo,
        CU_TENSOR_MAP_FLOAT_OOB_FILL_NONE);
    return m;
}

extern "C" void kernel_launch(void* const* d_in, const int* in_sizes, int n_in, void* d_out, int out_size) {
    void* fn = nullptr;
    cudaDriverEntryPointQueryResult qr;
    cudaGetDriverEntryPoint("cuTensorMapEncodeTiled", &fn, cudaEnableDefault, &qr);
    EncodeFn enc = (EncodeFn)fn;
    void* pX;
    cudaGetSymbolAddress(&pX, g_X);
    const CUtensorMapL2promotion P256 = CU_TENSOR_MAP_L2_PROMOTION_L2_256B, P0 = CU_TENSOR_MAP_L2_PROMOTION_NONE;

    const cuuint64_t dX[5] = {1024, 2, 4, 16, 16}, sX[4] = {2048, 32 * 2048, 2 * 2048, 128 * 2048};
    const cuuint32_t bX[5] = {64, 2, 4, 16, 1};
    CUtensorMap tmX = make_map(enc, d_in[3], 5, dX, sX, bX, CU_TENSOR_MAP_SWIZZLE_128B, P256);
    const cuuint64_t dXd[4] = {64, 2048, 2, 16}, sXd[3] = {2048, 64 * 2048, 128};
    const cuuint32_t bXd[4] = {64, 16, 2, 2};
    CUtensorMap tmXd = make_map(enc, d_in[3], 4, dXd, sXd, bXd, CU_TENSOR_MAP_SWIZZLE_128B, P256);
    const cuuint64_t dB[4] = {1024, 8, 4, 32}, sB[3] = {2048, 256 * 2048, 8 * 2048};
    const cuuint32_t bB4[4] = {64, 8, 2, 4};
    CUtensorMap tmBre = make_map(enc, d_in[6], 4, dB, sB, bB4, CU_TENSOR_MAP_SWIZZLE_128B, P256);
    CUtensorMap tmBim = make_map(enc, d_in[7], 4, dB, sB, bB4, CU_TENSOR_MAP_SWIZZLE_128B, P256);
    const cuuint64_t dC[5] = {1024, 2, 4, 2, 64}, sC[4] = {2048, 4 * 2048, 2 * 2048, 16 * 2048};
    const cuuint32_t bC[5] = {64, 2, 4, 2, 4};
    CUtensorMap tmCre = make_map(enc, d_in[8], 5, dC, sC, bC, CU_TENSOR_MAP_SWIZZLE_128B, P256);
    CUtensorMap tmCim = make_map(enc, d_in[9], 5, dC, sC, bC, CU_TENSOR_MAP_SWIZZLE_128B, P256);

    const cuuint64_t dU[2] = {8192, 256}, sU[1] = {16384};
    const cuuint32_t bU[2] = {64, 64};
    CUtensorMap tmUst = make_map(enc, pX, 2, dU, sU, bU, CU_TENSOR_MAP_SWIZZLE_128B, P0);
    const cuuint64_t dV[2] = {16384, 128}, sV[1] = {32768};
    const cuuint32_t bV[2] = {32, 128};
    CUtensorMap tmVst = make_map(enc, (uint8_t*)pX + (4 << 20), 2, dV, sV, bV, CU_TENSOR_MAP_SWIZZLE_NONE, P0);
    const cuuint64_t dF[2] = {512 * 1026 / 8, 4}, sF[1] = {512 * 1026};
    const cuuint32_t bF[2] = {WPITCH / 8, 4};
    CUtensorMap tmWr = make_map(enc, d_in[1], 2, dF, sF, bF, CU_TENSOR_MAP_SWIZZLE_NONE, P0, CU_TENSOR_MAP_DATA_TYPE_UINT64);
    CUtensorMap tmWi = make_map(enc, d_in[2], 2, dF, sF, bF, CU_TENSOR_MAP_SWIZZLE_NONE, P0, CU_TENSOR_MAP_DATA_TYPE_UINT64);

    const cuuint64_t dA[3] = {1024, 64, 32}, sA[2] = {32 * 2048, 2048};
    const cuuint32_t bA[3] = {32, 64, 1};
    CUtensorMap tmXa = make_map(enc, d_in[0], 3, dA, sA, bA, CU_TENSOR_MAP_SWIZZLE_64B, CU_TENSOR_MAP_L2_PROMOTION_L2_128B);

    Params p;
    p.wr = (const __nv_bfloat16*)d_in[1];
    p.wi = (const __nv_bfloat16*)d_in[2];
    p.lre = (const __nv_bfloat16*)d_in[4];
    p.lim = (const __nv_bfloat16*)d_in[5];
    p.ldt = (const __nv_bfloat16*)d_in[10];
    p.dsk = (const __nv_bfloat16*)d_in[11];
    p.out = (float*)d_out;
    int dev = 0, sms = 0;
    cudaGetDevice(&dev);
    cudaDeviceGetAttribute(&sms, cudaDevAttrMultiProcessorCount, dev);
    auto kernel = sms == 132 ? fused_kernel<true> : fused_kernel<false>;
    cudaFuncSetAttribute(kernel, cudaFuncAttributeMaxDynamicSharedMemorySize, SMEM_BYTES);
    kernel<<<132, 512, SMEM_BYTES>>>(tmX, tmBre, tmBim, tmCre, tmCim, tmXd, tmUst, tmVst, tmWr, tmWi, tmXa, p);
}
```

```cpp
#include <cuda_runtime.h>
#include <cuda.h>
#include <cuda_bf16.h>
#include <stdint.h>

#define NST 5
#define WPITCH 1056
#define OFF_P (NST * 32768)
#define OFF_F (OFF_P + 32768)
#define OFF_WD (OFF_F + 8192)
#define OFF_WM (OFF_WD + 8 * WPITCH)
#define OFF_BAR (OFF_F + 32768)
#define OFF_LAM (OFF_BAR + 432)
#define OFF_WSP (OFF_LAM + 2048)
#define OFF_PROF (OFF_WSP + 128)
#define SMEM_BYTES OFF_PROF
#define B_FULL 0
#define B_HL 40
#define B_EP 120
#define B_HR 128
#define B_XD 144
#define B_FG 160
#define B_WSP 168
#define B_WD 176
#define B_DONE 184
#define B_LD 192
#define B_RAW 200
#define B_LAM 208
#define B_IN 216
#define B_XIN 248
#define B_EMPTY 256
#define B_STG 320
#define B_WFREE 328
#define B_HOWN 336
#define B_STGU 368
#define B_P3M 384
#define B_EPOCH 416

#define XA_PACE 200
#define PACE_O 400
#define PACE_ON 3
#define TAB_T0 500
#define LAM_T0 2000
#define XA_N0 2
#define PACE_X 200
#define SKEW 4
#define SPIN_LIMIT (1u << 15)

__device__ __align__(1024) uint8_t g_X[8 << 20];
__device__ __align__(1024) uint8_t g_H[8 << 20];
__device__ __align__(1024) uint4 g_carry[16 * 512];
__device__ __align__(128) unsigned g_cnt[128];
__device__ __align__(128) unsigned g_epoch[132 * 8];

#define STAMP(i) do { } while (0)
#define STAMPO(i, o) do { } while (0)
#define STAMPW(a, b) do { } while (0)
#define STAMPX(a, b) do { } while (0)
#define STAMP5(i) do { } while (0)
#define STAMP3(i) do { } while (0)

#define TAB_FG 0
#define TAB_G 8192
#define TAB_F1 40960
#define TAB_SP 49152
#define TAB_TW1 65536
#define TAB_TW3 67584
#define TAB_PC 75776
__device__ __align__(1024) const uint32_t g_tab[19200] = {
0x80003d80,0x80003d80,0x80003d80,0x80003d80,0x80003d80,0x80003d80,0x80003d80,0x80003d80,0x80003d80,0x80003d80,0x80003d80,0x80003d80,0x80003d80,0x80003d80,0x80003d80,0x80003d80,
0x80003d80,0x80003d80,0x80003d80,0x80003d80,0x80003d80,0x80003d80,0x80003d80,0x80003d80,0x80003d80,0x80003d80,0x80003d80,0x80003d80,0x80003d80,0x80003d80,0x80003d80,0x80003d80,
0x3d353d35,0x3d35bd35,0xbd35bd35,0xbd353d35,0x80003d80,0x3d800000,0x8000bd80,0xbd800000,0x3d353d35,0x3d35bd35,0xbd35bd35,0xbd353d35,0x80003d80,0x3d800000,0x8000bd80,0xbd800000,
0x3d353d35,0x3d35bd35,0xbd35bd35,0xbd353d35,0x80003d80,0x3d800000,0x8000bd80,0xbd800000,0x3d353d35,0x3d35bd35,0xbd35bd35,0xbd353d35,0x80003d80,0x3d800000,0x8000bd80,0xbd800000,
0x3d800000,0x3d6dbcc4,0x3d35bd35,0x3cc4bd6d,0x3d7bbc48,0x3d55bd0e,0x3d0ebd55,0x3c48bd7b,0x80003d80,0x3cc43d6d,0x3d353d35,0x3d6d3cc4,0x3c483d7b,0x3d0e3d55,0x3d553d0e,0x3d7b3c48,
0xbd800000,0xbd6d3cc4,0xbd353d35,0xbcc43d6d,0xbd7b3c48,0xbd553d0e,0xbd0e3d55,0xbc483d7b,0x8000bd80,0xbcc4bd6d,0xbd35bd35,0xbd6dbcc4,0xbc48bd7b,0xbd0ebd55,0xbd55bd0e,0xbd7bbc48,
0x3d0ebd55,0xbd7bbc48,0x3c483d7b,0x3d55bd0e,0x3d800000,0xbcc4bd6d,0xbd353d35,0x3d6d3cc4,0x3d553d0e,0x3c48bd7b,0xbd7b3c48,0x3d0e3d55,0x80003d80,0x3d6dbcc4,0xbd35bd35,0xbcc43d6d,
0xbd0e3d55,0x3d7b3c48,0xbc48bd7b,0xbd553d0e,0xbd800000,0x3cc43d6d,0x3d35bd35,0xbd6dbcc4,0xbd55bd0e,0xbc483d7b,0x3d7bbc48,0xbd0ebd55,0x8000bd80,0xbd6d3cc4,0x3d353d35,0x3cc4bd6d,
0x80003d80,0x3d353d35,0x3d800000,0x3d35bd35,0x3cc43d6d,0x3d6d3cc4,0x3d6dbcc4,0x3cc4bd6d,0x8000bd80,0xbd35bd35,0xbd800000,0xbd353d35,0xbcc4bd6d,0xbd6dbcc4,0xbd6d3cc4,0xbcc43d6d,
0x80003d80,0x3d353d35,0x3d800000,0x3d35bd35,0x3cc43d6d,0x3d6d3cc4,0x3d6dbcc4,0x3cc4bd6d,0x8000bd80,0xbd35bd35,0xbd800000,0xbd353d35,0xbcc4bd6d,0xbd6dbcc4,0xbd6d3cc4,0xbcc43d6d,
0x3d6d3cc4,0xbcc4bd6d,0xbcc43d6d,0x3d6dbcc4,0x80003d80,0x3d35bd35,0xbd800000,0x3d353d35,0xbd6dbcc4,0x3cc43d6d,0x3cc4bd6d,0xbd6d3cc4,0x8000bd80,0xbd353d35,0x3d800000,0xbd35bd35,
0x3d6d3cc4,0xbcc4bd6d,0xbcc43d6d,0x3d6dbcc4,0x80003d80,0x3d35bd35,0xbd800000,0x3d353d35,0xbd6dbcc4,0x3cc43d6d,0x3cc4bd6d,0xbd6d3cc4,0x8000bd80,0xbd353d35,0x3d800000,0xbd35bd35,
0x3d800000,0x3cc4bd6d,0xbd35bd35,0xbd6d3cc4,0x3d55bd0e,0xbc48bd7b,0xbd7bbc48,0xbd0e3d55,0x8000bd80,0xbd6dbcc4,0xbd353d35,0x3cc43d6d,0xbd0ebd55,0xbd7b3c48,0xbc483d7b,0x3d553d0e,
0xbd800000,0xbcc43d6d,0x3d353d35,0x3d6dbcc4,0xbd553d0e,0x3c483d7b,0x3d7b3c48,0x3d0ebd55,0x80003d80,0x3d6d3cc4,0x3d35bd35,0xbcc4bd6d,0x3d0e3d55,0x3d7bbc48,0x3c48bd7b,0xbd55bd0e,
0x3c48bd7b,0xbd0e3d55,0x3d55bd0e,0xbd7b3c48,0x3d800000,0xbd6dbcc4,0x3d353d35,0xbcc4bd6d,0xbd7bbc48,0x3d553d0e,0xbd0ebd55,0x3c483d7b,0x8000bd80,0xbcc43d6d,0x3d35bd35,0xbd6d3cc4,
0xbc483d7b,0x3d0ebd55,0xbd553d0e,0x3d7bbc48,0xbd800000,0x3d6d3cc4,0xbd35bd35,0x3cc43d6d,0x3d7b3c48,0xbd55bd0e,0x3d0e3d55,0xbc48bd7b,0x80003d80,0x3cc4bd6d,0xbd353d35,0x3d6dbcc4,
0x3d800000,0x3d800000,0x3d800000,0x3d800000,0x3d800000,0x3d800000,0x3d800000,0x3d800000,0x3d800000,0x3d800000,0x3d800000,0x3d800000,0x3d800000,0x3d800000,0x3d800000,0x3d800000,
0x3d800000,0x3d800000,0x3d800000,0x3d800000,0x3d800000,0x3d800000,0x3d800000,0x3d800000,0x3d800000,0x3d800000,0x3d800000,0x3d800000,0x3d800000,0x3d800000,0x3d800000,0x3d800000,
0x3d35bd35,0xbd35bd35,0xbd353d35,0x3d353d35,0x3d800000,0xbd80,0xbd800000,0x3d80,0x3d35bd35,0xbd35bd35,0xbd353d35,0x3d353d35,0x3d800000,0xbd80,0xbd800000,0x3d80,
0x3d35bd35,0xbd35bd35,0xbd353d35,0x3d353d35,0x3d800000,0xbd80,0xbd800000,0x3d80,0x3d35bd35,0xbd35bd35,0xbd353d35,0x3d353d35,0x3d800000,0xbd80,0xbd800000,0x3d80,
0xbd80,0xbcc4bd6d,0xbd35bd35,0xbd6dbcc4,0xbc48bd7b,0xbd0ebd55,0xbd55bd0e,0xbd7bbc48,0x3d800000,0x3d6dbcc4,0x3d35bd35,0x3cc4bd6d,0x3d7bbc48,0x3d55bd0e,0x3d0ebd55,0x3c48bd7b,
0x3d80,0x3cc43d6d,0x3d353d35,0x3d6d3cc4,0x3c483d7b,0x3d0e3d55,0x3d553d0e,0x3d7b3c48,0xbd800000,0xbd6d3cc4,0xbd353d35,0xbcc43d6d,0xbd7b3c48,0xbd553d0e,0xbd0e3d55,0xbc483d7b,
0xbd55bd0e,0xbc483d7b,0x3d7bbc48,0xbd0ebd55,0xbd80,0xbd6d3cc4,0x3d353d35,0x3cc4bd6d,0x3d0ebd55,0xbd7bbc48,0x3c483d7b,0x3d55bd0e,0x3d800000,0xbcc4bd6d,0xbd353d35,0x3d6d3cc4,
0x3d553d0e,0x3c48bd7b,0xbd7b3c48,0x3d0e3d55,0x3d80,0x3d6dbcc4,0xbd35bd35,0xbcc43d6d,0xbd0e3d55,0x3d7b3c48,0xbc48bd7b,0xbd553d0e,0xbd800000,0x3cc43d6d,0x3d35bd35,0xbd6dbcc4,
0x3d800000,0x3d35bd35,0xbd80,0xbd35bd35,0x3d6dbcc4,0x3cc4bd6d,0xbcc4bd6d,0xbd6dbcc4,0xbd800000,0xbd353d35,0x3d80,0x3d353d35,0xbd6d3cc4,0xbcc43d6d,0x3cc43d6d,0x3d6d3cc4,
0x3d800000,0x3d35bd35,0xbd80,0xbd35bd35,0x3d6dbcc4,0x3cc4bd6d,0xbcc4bd6d,0xbd6dbcc4,0xbd800000,0xbd353d35,0x3d80,0x3d353d35,0xbd6d3cc4,0xbcc43d6d,0x3cc43d6d,0x3d6d3cc4,
0x3cc4bd6d,0xbd6d3cc4,0x3d6d3cc4,0xbcc4bd6d,0x3d800000,0xbd35bd35,0x3d80,0x3d35bd35,0xbcc43d6d,0x3d6dbcc4,0xbd6dbcc4,0x3cc43d6d,0xbd800000,0x3d353d35,0xbd80,0xbd353d35,
0x3cc4bd6d,0xbd6d3cc4,0x3d6d3cc4,0xbcc4bd6d,0x3d800000,0xbd35bd35,0x3d80,0x3d35bd35,0xbcc43d6d,0x3d6dbcc4,0xbd6dbcc4,0x3cc43d6d,0xbd800000,0x3d353d35,0xbd80,0xbd353d35,
0xbd80,0xbd6dbcc4,0xbd353d35,0x3cc43d6d,0xbd0ebd55,0xbd7b3c48,0xbc483d7b,0x3d553d0e,0xbd800000,0xbcc43d6d,0x3d353d35,0x3d6dbcc4,0xbd553d0e,0x3c483d7b,0x3d7b3c48,0x3d0ebd55,
0x3d80,0x3d6d3cc4,0x3d35bd35,0xbcc4bd6d,0x3d0e3d55,0x3d7bbc48,0x3c48bd7b,0xbd55bd0e,0x3d800000,0x3cc4bd6d,0xbd35bd35,0xbd6d3cc4,0x3d55bd0e,0xbc48bd7b,0xbd7bbc48,0xbd0e3d55,
0xbd7bbc48,0x3d553d0e,0xbd0ebd55,0x3c483d7b,0xbd80,0xbcc43d6d,0x3d35bd35,0xbd6d3cc4,0xbc483d7b,0x3d0ebd55,0xbd553d0e,0x3d7bbc48,0xbd800000,0x3d6d3cc4,0xbd35bd35,0x3cc43d6d,
0x3d7b3c48,0xbd55bd0e,0x3d0e3d55,0xbc48bd7b,0x3d80,0x3cc4bd6d,0xbd353d35,0x3d6dbcc4,0x3c48bd7b,0xbd0e3d55,0x3d55bd0e,0xbd7b3c48,0x3d800000,0xbd6dbcc4,0x3d353d35,0xbcc4bd6d,
0x80003d80,0x8000bd80,0x80003d80,0x8000bd80,0x3d800000,0xbd800000,0x3d800000,0xbd800000,0x80003d80,0x8000bd80,0x80003d80,0x8000bd80,0x3d800000,0xbd800000,0x3d800000,0xbd800000,
0x80003d80,0x8000bd80,0x80003d80,0x8000bd80,0x3d800000,0xbd800000,0x3d800000,0xbd800000,0x80003d80,0x8000bd80,0x80003d80,0x8000bd80,0x3d800000,0xbd800000,0x3d800000,0xbd800000,
0x3d35bd35,0x3d353d35,0xbd353d35,0xbd35bd35,0x80003d80,0xbd800000,0x8000bd80,0x3d800000,0x3d35bd35,0x3d353d35,0xbd353d35,0xbd35bd35,0x80003d80,0xbd800000,0x8000bd80,0x3d800000,
0x3d35bd35,0x3d353d35,0xbd353d35,0xbd35bd35,0x80003d80,0xbd800000,0x8000bd80,0x3d800000,0x3d35bd35,0x3d353d35,0xbd353d35,0xbd35bd35,0x80003d80,0xbd800000,0x8000bd80,0x3d800000,
0x3d800000,0xbd6d3cc4,0x3d35bd35,0xbcc43d6d,0xbc48bd7b,0x3d0e3d55,0xbd55bd0e,0x3d7b3c48,0x80003d80,0xbcc4bd6d,0x3d353d35,0xbd6dbcc4,0x3d7bbc48,0xbd553d0e,0x3d0ebd55,0xbc483d7b,
0xbd800000,0x3d6dbcc4,0xbd353d35,0x3cc4bd6d,0x3c483d7b,0xbd0ebd55,0x3d553d0e,0xbd7bbc48,0x8000bd80,0x3cc43d6d,0xbd35bd35,0x3d6d3cc4,0xbd7b3c48,0x3d55bd0e,0xbd0e3d55,0x3c48bd7b,
0xbd55bd0e,0x3c48bd7b,0x3d7bbc48,0x3d0e3d55,0x3d800000,0x3cc43d6d,0xbd353d35,0xbd6dbcc4,0x3d0ebd55,0x3d7b3c48,0x3c483d7b,0xbd553d0e,0x80003d80,0xbd6d3cc4,0xbd35bd35,0x3cc4bd6d,
0x3d553d0e,0xbc483d7b,0xbd7b3c48,0xbd0ebd55,0xbd800000,0xbcc4bd6d,0x3d35bd35,0x3d6d3cc4,0xbd0e3d55,0xbd7bbc48,0xbc48bd7b,0x3d55bd0e,0x8000bd80,0x3d6dbcc4,0x3d353d35,0xbcc43d6d,
0x80003d80,0xbd35bd35,0x3d800000,0xbd353d35,0x3d6dbcc4,0xbcc43d6d,0xbcc4bd6d,0x3d6d3cc4,0x8000bd80,0x3d353d35,0xbd800000,0x3d35bd35,0xbd6d3cc4,0x3cc4bd6d,0x3cc43d6d,0xbd6dbcc4,
0x80003d80,0xbd35bd35,0x3d800000,0xbd353d35,0x3d6dbcc4,0xbcc43d6d,0xbcc4bd6d,0x3d6d3cc4,0x8000bd80,0x3d353d35,0xbd800000,0x3d35bd35,0xbd6d3cc4,0x3cc4bd6d,0x3cc43d6d,0xbd6dbcc4,
0x3cc4bd6d,0x3d6dbcc4,0x3d6d3cc4,0x3cc43d6d,0x80003d80,0xbd353d35,0xbd800000,0xbd35bd35,0xbcc43d6d,0xbd6d3cc4,0xbd6dbcc4,0xbcc4bd6d,0x8000bd80,0x3d35bd35,0x3d800000,0x3d353d35,
0x3cc4bd6d,0x3d6dbcc4,0x3d6d3cc4,0x3cc43d6d,0x80003d80,0xbd353d35,0xbd800000,0xbd35bd35,0xbcc43d6d,0xbd6d3cc4,0xbd6dbcc4,0xbcc4bd6d,0x8000bd80,0x3d35bd35,0x3d800000,0x3d353d35,
0x3d800000,0xbcc43d6d,0xbd35bd35,0x3d6dbcc4,0xbd0ebd55,0x3d7bbc48,0xbc483d7b,0xbd55bd0e,0x8000bd80,0x3d6d3cc4,0xbd353d35,0xbcc4bd6d,0xbd553d0e,0xbc48bd7b,0x3d7b3c48,0xbd0e3d55,
0xbd800000,0x3cc4bd6d,0x3d353d35,0xbd6d3cc4,0x3d0e3d55,0xbd7b3c48,0x3c48bd7b,0x3d553d0e,0x80003d80,0xbd6dbcc4,0x3d35bd35,0x3cc43d6d,0x3d55bd0e,0x3c483d7b,0xbd7bbc48,0x3d0ebd55,
0xbd7bbc48,0xbd55bd0e,0xbd0ebd55,0xbc48bd7b,0x3d800000,0x3d6d3cc4,0x3d353d35,0x3cc43d6d,0xbc483d7b,0xbd0e3d55,0xbd553d0e,0xbd7b3c48,0x8000bd80,0x3cc4bd6d,0x3d35bd35,0x3d6dbcc4,
0x3d7b3c48,0x3d553d0e,0x3d0e3d55,0x3c483d7b,0xbd800000,0xbd6dbcc4,0xbd35bd35,0xbcc4bd6d,0x3c48bd7b,0x3d0ebd55,0x3d55bd0e,0x3d7bbc48,0x80003d80,0xbcc43d6d,0xbd353d35,0xbd6d3cc4,
0x3d800000,0xbd800000,0x3d800000,0xbd800000,0xbd80,0x3d80,0xbd80,0x3d80,0x3d800000,0xbd800000,0x3d800000,0xbd800000,0xbd80,0x3d80,0xbd80,0x3d80,
0x3d800000,0xbd800000,0x3d800000,0xbd800000,0xbd80,0x3d80,0xbd80,0x3d80,0x3d800000,0xbd800000,0x3d800000,0xbd800000,0xbd80,0x3d80,0xbd80,0x3d80,
0xbd35bd35,0x3d35bd35,0x3d353d35,0xbd353d35,0x3d800000,0x3d80,0xbd800000,0xbd80,0xbd35bd35,0x3d35bd35,0x3d353d35,0xbd353d35,0x3d800000,0x3d80,0xbd800000,0xbd80,
0xbd35bd35,0x3d35bd35,0x3d353d35,0xbd353d35,0x3d800000,0x3d80,0xbd800000,0xbd80,0xbd35bd35,0x3d35bd35,0x3d353d35,0xbd353d35,0x3d800000,0x3d80,0xbd800000,0xbd80,
0xbd80,0x3cc43d6d,0xbd35bd35,0x3d6d3cc4,0xbd7b3c48,0x3d55bd0e,0xbd0e3d55,0x3c48bd7b,0x3d800000,0xbd6d3cc4,0x3d35bd35,0xbcc43d6d,0xbc48bd7b,0x3d0e3d55,0xbd55bd0e,0x3d7b3c48,
0x3d80,0xbcc4bd6d,0x3d353d35,0xbd6dbcc4,0x3d7bbc48,0xbd553d0e,0x3d0ebd55,0xbc483d7b,0xbd800000,0x3d6dbcc4,0xbd353d35,0x3cc4bd6d,0x3c483d7b,0xbd0ebd55,0x3d553d0e,0xbd7bbc48,
0xbd0e3d55,0xbd7bbc48,0xbc48bd7b,0x3d55bd0e,0xbd80,0x3d6dbcc4,0x3d353d35,0xbcc43d6d,0xbd55bd0e,0x3c48bd7b,0x3d7bbc48,0x3d0e3d55,0x3d800000,0x3cc43d6d,0xbd353d35,0xbd6dbcc4,
0x3d0ebd55,0x3d7b3c48,0x3c483d7b,0xbd553d0e,0x3d80,0xbd6d3cc4,0xbd35bd35,0x3cc4bd6d,0x3d553d0e,0xbc483d7b,0xbd7b3c48,0xbd0ebd55,0xbd800000,0xbcc4bd6d,0x3d35bd35,0x3d6d3cc4,
0x3d800000,0xbd353d35,0xbd80,0x3d353d35,0xbcc4bd6d,0x3d6d3cc4,0xbd6d3cc4,0x3cc4bd6d,0xbd800000,0x3d35bd35,0x3d80,0xbd35bd35,0x3cc43d6d,0xbd6dbcc4,0x3d6dbcc4,0xbcc43d6d,
0x3d800000,0xbd353d35,0xbd80,0x3d353d35,0xbcc4bd6d,0x3d6d3cc4,0xbd6d3cc4,0x3cc4bd6d,0xbd800000,0x3d35bd35,0x3d80,0xbd35bd35,0x3cc43d6d,0xbd6dbcc4,0x3d6dbcc4,0xbcc43d6d,
0xbd6dbcc4,0xbcc4bd6d,0x3cc4bd6d,0x3d6dbcc4,0x3d800000,0x3d353d35,0x3d80,0xbd353d35,0x3d6d3cc4,0x3cc43d6d,0xbcc43d6d,0xbd6d3cc4,0xbd800000,0xbd35bd35,0xbd80,0x3d35bd35,
0xbd6dbcc4,0xbcc4bd6d,0x3cc4bd6d,0x3d6dbcc4,0x3d800000,0x3d353d35,0x3d80,0xbd353d35,0x3d6d3cc4,0x3cc43d6d,0xbcc43d6d,0xbd6d3cc4,0xbd800000,0xbd35bd35,0xbd80,0x3d35bd35,
0xbd80,0x3d6d3cc4,0xbd353d35,0xbcc4bd6d,0xbd553d0e,0xbc48bd7b,0x3d7b3c48,0xbd0e3d55,0xbd800000,0x3cc4bd6d,0x3d353d35,0xbd6d3cc4,0x3d0e3d55,0xbd7b3c48,0x3c48bd7b,0x3d553d0e,
0x3d80,0xbd6dbcc4,0x3d35bd35,0x3cc43d6d,0x3d55bd0e,0x3c483d7b,0xbd7bbc48,0x3d0ebd55,0x3d800000,0xbcc43d6d,0xbd35bd35,0x3d6dbcc4,0xbd0ebd55,0x3d7bbc48,0xbc483d7b,0xbd55bd0e,
0xbc483d7b,0xbd0e3d55,0xbd553d0e,0xbd7b3c48,0xbd80,0x3cc4bd6d,0x3d35bd35,0x3d6dbcc4,0x3d7b3c48,0x3d553d0e,0x3d0e3d55,0x3c483d7b,0xbd800000,0xbd6dbcc4,0xbd35bd35,0xbcc4bd6d,
0x3c48bd7b,0x3d0ebd55,0x3d55bd0e,0x3d7bbc48,0x3d80,0xbcc43d6d,0xbd353d35,0xbd6d3cc4,0xbd7bbc48,0xbd55bd0e,0xbd0ebd55,0xbc48bd7b,0x3d800000,0x3d6d3cc4,0x3d353d35,0x3cc43d6d,
0x80003d80,0x80003d80,0x80003d80,0x80003d80,0x8000bd80,0x8000bd80,0x8000bd80,0x8000bd80,0x80003d80,0x80003d80,0x80003d80,0x80003d80,0x8000bd80,0x8000bd80,0x8000bd80,0x8000bd80,
0x80003d80,0x80003d80,0x80003d80,0x80003d80,0x8000bd80,0x8000bd80,0x8000bd80,0x8000bd80,0x80003d80,0x80003d80,0x80003d80,0x80003d80,0x8000bd80,0x8000bd80,0x8000bd80,0x8000bd80,
0xbd35bd35,0xbd353d35,0x3d353d35,0x3d35bd35,0x80003d80,0x3d800000,0x8000bd80,0xbd800000,0xbd35bd35,0xbd353d35,0x3d353d35,0x3d35bd35,0x80003d80,0x3d800000,0x8000bd80,0xbd800000,
0xbd35bd35,0xbd353d35,0x3d353d35,0x3d35bd35,0x80003d80,0x3d800000,0x8000bd80,0xbd800000,0xbd35bd35,0xbd353d35,0x3d353d35,0x3d35bd35,0x80003d80,0x3d800000,0x8000bd80,0xbd800000,
0x3d800000,0x3d6dbcc4,0x3d35bd35,0x3cc4bd6d,0xbd7b3c48,0xbd553d0e,0xbd0e3d55,0xbc483d7b,0x80003d80,0x3cc43d6d,0x3d353d35,0x3d6d3cc4,0xbc48bd7b,0xbd0ebd55,0xbd55bd0e,0xbd7bbc48,
0xbd800000,0xbd6d3cc4,0xbd353d35,0xbcc43d6d,0x3d7bbc48,0x3d55bd0e,0x3d0ebd55,0x3c48bd7b,0x8000bd80,0xbcc4bd6d,0xbd35bd35,0xbd6dbcc4,0x3c483d7b,0x3d0e3d55,0x3d553d0e,0x3d7b3c48,
0xbd0e3d55,0x3d7b3c48,0xbc48bd7b,0xbd553d0e,0x3d800000,0xbcc4bd6d,0xbd353d35,0x3d6d3cc4,0xbd55bd0e,0xbc483d7b,0x3d7bbc48,0xbd0ebd55,0x80003d80,0x3d6dbcc4,0xbd35bd35,0xbcc43d6d,
0x3d0ebd55,0xbd7bbc48,0x3c483d7b,0x3d55bd0e,0xbd800000,0x3cc43d6d,0x3d35bd35,0xbd6dbcc4,0x3d553d0e,0x3c48bd7b,0xbd7b3c48,0x3d0e3d55,0x8000bd80,0xbd6d3cc4,0x3d353d35,0x3cc4bd6d,
0x80003d80,0x3d353d35,0x3d800000,0x3d35bd35,0xbcc4bd6d,0xbd6dbcc4,0xbd6d3cc4,0xbcc43d6d,0x8000bd80,0xbd35bd35,0xbd800000,0xbd353d35,0x3cc43d6d,0x3d6d3cc4,0x3d6dbcc4,0x3cc4bd6d,
0x80003d80,0x3d353d35,0x3d800000,0x3d35bd35,0xbcc4bd6d,0xbd6dbcc4,0xbd6d3cc4,0xbcc43d6d,0x8000bd80,0xbd35bd35,0xbd800000,0xbd353d35,0x3cc43d6d,0x3d6d3cc4,0x3d6dbcc4,0x3cc4bd6d,
0xbd6dbcc4,0x3cc43d6d,0x3cc4bd6d,0xbd6d3cc4,0x80003d80,0x3d35bd35,0xbd800000,0x3d353d35,0x3d6d3cc4,0xbcc4bd6d,0xbcc43d6d,0x3d6dbcc4,0x8000bd80,0xbd353d35,0x3d800000,0xbd35bd35,
0xbd6dbcc4,0x3cc43d6d,0x3cc4bd6d,0xbd6d3cc4,0x80003d80,0x3d35bd35,0xbd800000,0x3d353d35,0x3d6d3cc4,0xbcc4bd6d,0xbcc43d6d,0x3d6dbcc4,0x8000bd80,0xbd353d35,0x3d800000,0xbd35bd35,
0x3d800000,0x3cc4bd6d,0xbd35bd35,0xbd6d3cc4,0xbd553d0e,0x3c483d7b,0x3d7b3c48,0x3d0ebd55,0x8000bd80,0xbd6dbcc4,0xbd353d35,0x3cc43d6d,0x3d0e3d55,0x3d7bbc48,0x3c48bd7b,0xbd55bd0e,
0xbd800000,0xbcc43d6d,0x3d353d35,0x3d6dbcc4,0x3d55bd0e,0xbc48bd7b,0xbd7bbc48,0xbd0e3d55,0x80003d80,0x3d6d3cc4,0x3d35bd35,0xbcc4bd6d,0xbd0ebd55,0xbd7b3c48,0xbc483d7b,0x3d553d0e,
0xbc483d7b,0x3d0ebd55,0xbd553d0e,0x3d7bbc48,0x3d800000,0xbd6dbcc4,0x3d353d35,0xbcc4bd6d,0x3d7b3c48,0xbd55bd0e,0x3d0e3d55,0xbc48bd7b,0x8000bd80,0xbcc43d6d,0x3d35bd35,0xbd6d3cc4,
0x3c48bd7b,0xbd0e3d55,0x3d55bd0e,0xbd7b3c48,0xbd800000,0x3d6d3cc4,0xbd35bd35,0x3cc43d6d,0xbd7bbc48,0x3d553d0e,0xbd0ebd55,0x3c483d7b,0x80003d80,0x3cc4bd6d,0xbd353d35,0x3d6dbcc4,
0x3d800000,0x3d800000,0x3d800000,0x3d800000,0xbd800000,0xbd800000,0xbd800000,0xbd800000,0x3d800000,0x3d800000,0x3d800000,0x3d800000,0xbd800000,0xbd800000,0xbd800000,0xbd800000,
0x3d800000,0x3d800000,0x3d800000,0x3d800000,0xbd800000,0xbd800000,0xbd800000,0xbd800000,0x3d800000,0x3d800000,0x3d800000,0x3d800000,0xbd800000,0xbd800000,0xbd800000,0xbd800000,
0xbd353d35,0x3d353d35,0x3d35bd35,0xbd35bd35,0x3d800000,0xbd80,0xbd800000,0x3d80,0xbd353d35,0x3d353d35,0x3d35bd35,0xbd35bd35,0x3d800000,0xbd80,0xbd800000,0x3d80,
0xbd353d35,0x3d353d35,0x3d35bd35,0xbd35bd35,0x3d800000,0xbd80,0xbd800000,0x3d80,0xbd353d35,0x3d353d35,0x3d35bd35,0xbd35bd35,0x3d800000,0xbd80,0xbd800000,0x3d80,
0xbd80,0xbcc4bd6d,0xbd35bd35,0xbd6dbcc4,0x3c483d7b,0x3d0e3d55,0x3d553d0e,0x3d7b3c48,0x3d800000,0x3d6dbcc4,0x3d35bd35,0x3cc4bd6d,0xbd7b3c48,0xbd553d0e,0xbd0e3d55,0xbc483d7b,
0x3d80,0x3cc43d6d,0x3d353d35,0x3d6d3cc4,0xbc48bd7b,0xbd0ebd55,0xbd55bd0e,0xbd7bbc48,0xbd800000,0xbd6d3cc4,0xbd353d35,0xbcc43d6d,0x3d7bbc48,0x3d55bd0e,0x3d0ebd55,0x3c48bd7b,
0x3d553d0e,0x3c48bd7b,0xbd7b3c48,0x3d0e3d55,0xbd80,0xbd6d3cc4,0x3d353d35,0x3cc4bd6d,0xbd0e3d55,0x3d7b3c48,0xbc48bd7b,0xbd553d0e,0x3d800000,0xbcc4bd6d,0xbd353d35,0x3d6d3cc4,
0xbd55bd0e,0xbc483d7b,0x3d7bbc48,0xbd0ebd55,0x3d80,0x3d6dbcc4,0xbd35bd35,0xbcc43d6d,0x3d0ebd55,0xbd7bbc48,0x3c483d7b,0x3d55bd0e,0xbd800000,0x3cc43d6d,0x3d35bd35,0xbd6dbcc4,
0x3d800000,0x3d35bd35,0xbd80,0xbd35bd35,0xbd6d3cc4,0xbcc43d6d,0x3cc43d6d,0x3d6d3cc4,0xbd800000,0xbd353d35,0x3d80,0x3d353d35,0x3d6dbcc4,0x3cc4bd6d,0xbcc4bd6d,0xbd6dbcc4,
0x3d800000,0x3d35bd35,0xbd80,0xbd35bd35,0xbd6d3cc4,0xbcc43d6d,0x3cc43d6d,0x3d6d3cc4,0xbd800000,0xbd353d35,0x3d80,0x3d353d35,0x3d6dbcc4,0x3cc4bd6d,0xbcc4bd6d,0xbd6dbcc4,
0xbcc43d6d,0x3d6dbcc4,0xbd6dbcc4,0x3cc43d6d,0x3d800000,0xbd35bd35,0x3d80,0x3d35bd35,0x3cc4bd6d,0xbd6d3cc4,0x3d6d3cc4,0xbcc4bd6d,0xbd800000,0x3d353d35,0xbd80,0xbd353d35,
0xbcc43d6d,0x3d6dbcc4,0xbd6dbcc4,0x3cc43d6d,0x3d800000,0xbd35bd35,0x3d80,0x3d35bd35,0x3cc4bd6d,0xbd6d3cc4,0x3d6d3cc4,0xbcc4bd6d,0xbd800000,0x3d353d35,0xbd80,0xbd353d35,
0xbd80,0xbd6dbcc4,0xbd353d35,0x3cc43d6d,0x3d0e3d55,0x3d7bbc48,0x3c48bd7b,0xbd55bd0e,0xbd800000,0xbcc43d6d,0x3d353d35,0x3d6dbcc4,0x3d55bd0e,0xbc48bd7b,0xbd7bbc48,0xbd0e3d55,
0x3d80,0x3d6d3cc4,0x3d35bd35,0xbcc4bd6d,0xbd0ebd55,0xbd7b3c48,0xbc483d7b,0x3d553d0e,0x3d800000,0x3cc4bd6d,0xbd35bd35,0xbd6d3cc4,0xbd553d0e,0x3c483d7b,0x3d7b3c48,0x3d0ebd55,
0x3d7b3c48,0xbd55bd0e,0x3d0e3d55,0xbc48bd7b,0xbd80,0xbcc43d6d,0x3d35bd35,0xbd6d3cc4,0x3c48bd7b,0xbd0e3d55,0x3d55bd0e,0xbd7b3c48,0xbd800000,0x3d6d3cc4,0xbd35bd35,0x3cc43d6d,
0xbd7bbc48,0x3d553d0e,0xbd0ebd55,0x3c483d7b,0x3d80,0x3cc4bd6d,0xbd353d35,0x3d6dbcc4,0xbc483d7b,0x3d0ebd55,0xbd553d0e,0x3d7bbc48,0x3d800000,0xbd6dbcc4,0x3d353d35,0xbcc4bd6d,
0x80003d80,0x8000bd80,0x80003d80,0x8000bd80,0xbd800000,0x3d800000,0xbd800000,0x3d800000,0x80003d80,0x8000bd80,0x80003d80,0x8000bd80,0xbd800000,0x3d800000,0xbd800000,0x3d800000,
0x80003d80,0x8000bd80,0x80003d80,0x8000bd80,0xbd800000,0x3d800000,0xbd800000,0x3d800000,0x80003d80,0x8000bd80,0x80003d80,0x8000bd80,0xbd800000,0x3d800000,0xbd800000,0x3d800000,
0xbd353d35,0xbd35bd35,0x3d35bd35,0x3d353d35,0x80003d80,0xbd800000,0x8000bd80,0x3d800000,0xbd353d35,0xbd35bd35,0x3d35bd35,0x3d353d35,0x80003d80,0xbd800000,0x8000bd80,0x3d800000,
0xbd353d35,0xbd35bd35,0x3d35bd35,0x3d353d35,0x80003d80,0xbd800000,0x8000bd80,0x3d800000,0xbd353d35,0xbd35bd35,0x3d35bd35,0x3d353d35,0x80003d80,0xbd800000,0x8000bd80,0x3d800000,
0x3d800000,0xbd6d3cc4,0x3d35bd35,0xbcc43d6d,0x3c483d7b,0xbd0ebd55,0x3d553d0e,0xbd7bbc48,0x80003d80,0xbcc4bd6d,0x3d353d35,0xbd6dbcc4,0xbd7b3c48,0x3d55bd0e,0xbd0e3d55,0x3c48bd7b,
0xbd800000,0x3d6dbcc4,0xbd353d35,0x3cc4bd6d,0xbc48bd7b,0x3d0e3d55,0xbd55bd0e,0x3d7b3c48,0x8000bd80,0x3cc43d6d,0xbd35bd35,0x3d6d3cc4,0x3d7bbc48,0xbd553d0e,0x3d0ebd55,0xbc483d7b,
0x3d553d0e,0xbc483d7b,0xbd7b3c48,0xbd0ebd55,0x3d800000,0x3cc43d6d,0xbd353d35,0xbd6dbcc4,0xbd0e3d55,0xbd7bbc48,0xbc48bd7b,0x3d55bd0e,0x80003d80,0xbd6d3cc4,0xbd35bd35,0x3cc4bd6d,
0xbd55bd0e,0x3c48bd7b,0x3d7bbc48,0x3d0e3d55,0xbd800000,0xbcc4bd6d,0x3d35bd35,0x3d6d3cc4,0x3d0ebd55,0x3d7b3c48,0x3c483d7b,0xbd553d0e,0x8000bd80,0x3d6dbcc4,0x3d353d35,0xbcc43d6d,
0x80003d80,0xbd35bd35,0x3d800000,0xbd353d35,0xbd6d3cc4,0x3cc4bd6d,0x3cc43d6d,0xbd6dbcc4,0x8000bd80,0x3d353d35,0xbd800000,0x3d35bd35,0x3d6dbcc4,0xbcc43d6d,0xbcc4bd6d,0x3d6d3cc4,
0x80003d80,0xbd35bd35,0x3d800000,0xbd353d35,0xbd6d3cc4,0x3cc4bd6d,0x3cc43d6d,0xbd6dbcc4,0x8000bd80,0x3d353d35,0xbd800000,0x3d35bd35,0x3d6dbcc4,0xbcc43d6d,0xbcc4bd6d,0x3d6d3cc4,
0xbcc43d6d,0xbd6d3cc4,0xbd6dbcc4,0xbcc4bd6d,0x80003d80,0xbd353d35,0xbd800000,0xbd35bd35,0x3cc4bd6d,0x3d6dbcc4,0x3d6d3cc4,0x3cc43d6d,0x8000bd80,0x3d35bd35,0x3d800000,0x3d353d35,
0xbcc43d6d,0xbd6d3cc4,0xbd6dbcc4,0xbcc4bd6d,0x80003d80,0xbd353d35,0xbd800000,0xbd35bd35,0x3cc4bd6d,0x3d6dbcc4,0x3d6d3cc4,0x3cc43d6d,0x8000bd80,0x3d35bd35,0x3d800000,0x3d353d35,
0x3d800000,0xbcc43d6d,0xbd35bd35,0x3d6dbcc4,0x3d0e3d55,0xbd7b3c48,0x3c48bd7b,0x3d553d0e,0x8000bd80,0x3d6d3cc4,0xbd353d35,0xbcc4bd6d,0x3d55bd0e,0x3c483d7b,0xbd7bbc48,0x3d0ebd55,
0xbd800000,0x3cc4bd6d,0x3d353d35,0xbd6d3cc4,0xbd0ebd55,0x3d7bbc48,0xbc483d7b,0xbd55bd0e,0x80003d80,0xbd6dbcc4,0x3d35bd35,0x3cc43d6d,0xbd553d0e,0xbc48bd7b,0x3d7b3c48,0xbd0e3d55,
0x3d7b3c48,0x3d553d0e,0x3d0e3d55,0x3c483d7b,0x3d800000,0x3d6d3cc4,0x3d353d35,0x3cc43d6d,0x3c48bd7b,0x3d0ebd55,0x3d55bd0e,0x3d7bbc48,0x8000bd80,0x3cc4bd6d,0x3d35bd35,0x3d6dbcc4,
0xbd7bbc48,0xbd55bd0e,0xbd0ebd55,0xbc48bd7b,0xbd800000,0xbd6dbcc4,0xbd35bd35,0xbcc4bd6d,0xbc483d7b,0xbd0e3d55,0xbd553d0e,0xbd7b3c48,0x80003d80,0xbcc43d6d,0xbd353d35,0xbd6d3cc4,
0x3d800000,0xbd800000,0x3d800000,0xbd800000,0x3d80,0xbd80,0x3d80,0xbd80,0x3d800000,0xbd800000,0x3d800000,0xbd800000,0x3d80,0xbd80,0x3d80,0xbd80,
0x3d800000,0xbd800000,0x3d800000,0xbd800000,0x3d80,0xbd80,0x3d80,0xbd80,0x3d800000,0xbd800000,0x3d800000,0xbd800000,0x3d80,0xbd80,0x3d80,0xbd80,
0x3d353d35,0xbd353d35,0xbd35bd35,0x3d35bd35,0x3d800000,0x3d80,0xbd800000,0xbd80,0x3d353d35,0xbd353d35,0xbd35bd35,0x3d35bd35,0x3d800000,0x3d80,0xbd800000,0xbd80,
0x3d353d35,0xbd353d35,0xbd35bd35,0x3d35bd35,0x3d800000,0x3d80,0xbd800000,0xbd80,0x3d353d35,0xbd353d35,0xbd35bd35,0x3d35bd35,0x3d800000,0x3d80,0xbd800000,0xbd80,
0xbd80,0x3cc43d6d,0xbd35bd35,0x3d6d3cc4,0x3d7bbc48,0xbd553d0e,0x3d0ebd55,0xbc483d7b,0x3d800000,0xbd6d3cc4,0x3d35bd35,0xbcc43d6d,0x3c483d7b,0xbd0ebd55,0x3d553d0e,0xbd7bbc48,
0x3d80,0xbcc4bd6d,0x3d353d35,0xbd6dbcc4,0xbd7b3c48,0x3d55bd0e,0xbd0e3d55,0x3c48bd7b,0xbd800000,0x3d6dbcc4,0xbd353d35,0x3cc4bd6d,0xbc48bd7b,0x3d0e3d55,0xbd55bd0e,0x3d7b3c48,
0x3d0ebd55,0x3d7b3c48,0x3c483d7b,0xbd553d0e,0xbd80,0x3d6dbcc4,0x3d353d35,0xbcc43d6d,0x3d553d0e,0xbc483d7b,0xbd7b3c48,0xbd0ebd55,0x3d800000,0x3cc43d6d,0xbd353d35,0xbd6dbcc4,
0xbd0e3d55,0xbd7bbc48,0xbc48bd7b,0x3d55bd0e,0x3d80,0xbd6d3cc4,0xbd35bd35,0x3cc4bd6d,0xbd55bd0e,0x3c48bd7b,0x3d7bbc48,0x3d0e3d55,0xbd800000,0xbcc4bd6d,0x3d35bd35,0x3d6d3cc4,
0x3d800000,0xbd353d35,0xbd80,0x3d353d35,0x3cc43d6d,0xbd6dbcc4,0x3d6dbcc4,0xbcc43d6d,0xbd800000,0x3d35bd35,0x3d80,0xbd35bd35,0xbcc4bd6d,0x3d6d3cc4,0xbd6d3cc4,0x3cc4bd6d,
0x3d800000,0xbd353d35,0xbd80,0x3d353d35,0x3cc43d6d,0xbd6dbcc4,0x3d6dbcc4,0xbcc43d6d,0xbd800000,0x3d35bd35,0x3d80,0xbd35bd35,0xbcc4bd6d,0x3d6d3cc4,0xbd6d3cc4,0x3cc4bd6d,
0x3d6d3cc4,0x3cc43d6d,0xbcc43d6d,0xbd6d3cc4,0x3d800000,0x3d353d35,0x3d80,0xbd353d35,0xbd6dbcc4,0xbcc4bd6d,0x3cc4bd6d,0x3d6dbcc4,0xbd800000,0xbd35bd35,0xbd80,0x3d35bd35,
0x3d6d3cc4,0x3cc43d6d,0xbcc43d6d,0xbd6d3cc4,0x3d800000,0x3d353d35,0x3d80,0xbd353d35,0xbd6dbcc4,0xbcc4bd6d,0x3cc4bd6d,0x3d6dbcc4,0xbd800000,0xbd35bd35,0xbd80,0x3d35bd35,
0xbd80,0x3d6d3cc4,0xbd353d35,0xbcc4bd6d,0x3d55bd0e,0x3c483d7b,0xbd7bbc48,0x3d0ebd55,0xbd800000,0x3cc4bd6d,0x3d353d35,0xbd6d3cc4,0xbd0ebd55,0x3d7bbc48,0xbc483d7b,0xbd55bd0e,
0x3d80,0xbd6dbcc4,0x3d35bd35,0x3cc43d6d,0xbd553d0e,0xbc48bd7b,0x3d7b3c48,0xbd0e3d55,0x3d800000,0xbcc43d6d,0xbd35bd35,0x3d6dbcc4,0x3d0e3d55,0xbd7b3c48,0x3c48bd7b,0x3d553d0e,
0x3c48bd7b,0x3d0ebd55,0x3d55bd0e,0x3d7bbc48,0xbd80,0x3cc4bd6d,0x3d35bd35,0x3d6dbcc4,0xbd7bbc48,0xbd55bd0e,0xbd0ebd55,0xbc48bd7b,0xbd800000,0xbd6dbcc4,0xbd35bd35,0xbcc4bd6d,
0xbc483d7b,0xbd0e3d55,0xbd553d0e,0xbd7b3c48,0x3d80,0xbcc43d6d,0xbd353d35,0xbd6d3cc4,0x3d7b3c48,0x3d553d0e,0x3d0e3d55,0x3c483d7b,0x3d800000,0x3d6d3cc4,0x3d353d35,0x3cc43d6d,
0x3d80,0x3d80,0x3d80,0x3d80,0x3d80,0x3d80,0x3d80,0x3d80,0x3d80,0x3d80,0x3d80,0x3d80,0x3d80,0x3d80,0x3d80,0x3d80,
0x3d80,0x3d80,0x3d80,0x3d80,0x3d80,0x3d80,0x3d80,0x3d80,0x3d80,0x3d80,0x3d80,0x3d80,0x3d80,0x3d80,0x3d80,0x3d80,
0xbd353d35,0xbd553d0e,0xbd6d3cc4,0xbd7b3c48,0x3d80,0xbc483d7b,0xbcc43d6d,0xbd0e3d55,0xbd35bd35,0xbd0ebd55,0xbcc4bd6d,0xbc48bd7b,0xbd800000,0xbd7bbc48,0xbd6dbcc4,0xbd55bd0e,
0x3d35bd35,0x3d55bd0e,0x3d6dbcc4,0x3d7bbc48,0xbd80,0x3c48bd7b,0x3cc4bd6d,0x3d0ebd55,0x3d353d35,0x3d0e3d55,0x3cc43d6d,0x3c483d7b,0x3d800000,0x3d7b3c48,0x3d6d3cc4,0x3d553d0e,
0xbd80,0x3cc4bd6d,0x3d35bd35,0x3d6dbcc4,0x3d800000,0x3d6d3cc4,0x3d353d35,0x3cc43d6d,0x3d80,0xbcc43d6d,0xbd353d35,0xbd6d3cc4,0xbd800000,0xbd6dbcc4,0xbd35bd35,0xbcc4bd6d,
0xbd80,0x3cc4bd6d,0x3d35bd35,0x3d6dbcc4,0x3d800000,0x3d6d3cc4,0x3d353d35,0x3cc43d6d,0x3d80,0xbcc43d6d,0xbd353d35,0xbd6d3cc4,0xbd800000,0xbd6dbcc4,0xbd35bd35,0xbcc4bd6d,
0xbd353d35,0xbd7b3c48,0xbd6dbcc4,0xbd0ebd55,0x3d800000,0x3d553d0e,0x3cc43d6d,0xbc483d7b,0xbd35bd35,0xbc48bd7b,0x3cc4bd6d,0x3d55bd0e,0x3d80,0xbd0e3d55,0xbd6d3cc4,0xbd7bbc48,
0x3d35bd35,0x3d7bbc48,0x3d6d3cc4,0x3d0e3d55,0xbd800000,0xbd55bd0e,0xbcc4bd6d,0x3c48bd7b,0x3d353d35,0x3c483d7b,0xbcc43d6d,0xbd553d0e,0xbd80,0x3d0ebd55,0x3d6dbcc4,0x3d7b3c48,
0x3d80,0xbd353d35,0xbd800000,0xbd35bd35,0xbd80,0x3d35bd35,0x3d800000,0x3d353d35,0x3d80,0xbd353d35,0xbd800000,0xbd35bd35,0xbd80,0x3d35bd35,0x3d800000,0x3d353d35,
0x3d80,0xbd353d35,0xbd800000,0xbd35bd35,0xbd80,0x3d35bd35,0x3d800000,0x3d353d35,0x3d80,0xbd353d35,0xbd800000,0xbd35bd35,0xbd80,0x3d35bd35,0x3d800000,0x3d353d35,
0xbd353d35,0xbd7bbc48,0xbcc4bd6d,0x3d0ebd55,0xbd80,0x3d55bd0e,0x3d6d3cc4,0x3c483d7b,0xbd35bd35,0x3c48bd7b,0x3d6dbcc4,0x3d553d0e,0x3d800000,0x3d0e3d55,0xbcc43d6d,0xbd7b3c48,
0x3d35bd35,0x3d7b3c48,0x3cc43d6d,0xbd0e3d55,0x3d80,0xbd553d0e,0xbd6dbcc4,0xbc48bd7b,0x3d353d35,0xbc483d7b,0xbd6d3cc4,0xbd55bd0e,0xbd800000,0xbd0ebd55,0x3cc4bd6d,0x3d7bbc48,
0xbd80,0x3d6dbcc4,0x3d353d35,0xbcc43d6d,0xbd800000,0xbcc4bd6d,0x3d35bd35,0x3d6d3cc4,0x3d80,0xbd6d3cc4,0xbd35bd35,0x3cc4bd6d,0x3d800000,0x3cc43d6d,0xbd353d35,0xbd6dbcc4,
0xbd80,0x3d6dbcc4,0x3d353d35,0xbcc43d6d,0xbd800000,0xbcc4bd6d,0x3d35bd35,0x3d6d3cc4,0x3d80,0xbd6d3cc4,0xbd35bd35,0x3cc4bd6d,0x3d800000,0x3cc43d6d,0xbd353d35,0xbd6dbcc4,
0xbd353d35,0xbd55bd0e,0x3cc4bd6d,0x3d7b3c48,0xbd800000,0xbc48bd7b,0x3d6dbcc4,0x3d0e3d55,0xbd35bd35,0x3d0ebd55,0x3d6d3cc4,0xbc483d7b,0xbd80,0x3d7bbc48,0x3cc43d6d,0xbd553d0e,
0x3d35bd35,0x3d553d0e,0xbcc43d6d,0xbd7bbc48,0x3d800000,0x3c483d7b,0xbd6d3cc4,0xbd0ebd55,0x3d353d35,0xbd0e3d55,0xbd6dbcc4,0x3c48bd7b,0x3d80,0xbd7b3c48,0xbcc4bd6d,0x3d55bd0e,
0xbd800000,0xbd800000,0xbd800000,0xbd800000,0xbd800000,0xbd800000,0xbd800000,0xbd800000,0xbd800000,0xbd800000,0xbd800000,0xbd800000,0xbd800000,0xbd800000,0xbd800000,0xbd800000,
0xbd800000,0xbd800000,0xbd800000,0xbd800000,0xbd800000,0xbd800000,0xbd800000,0xbd800000,0xbd800000,0xbd800000,0xbd800000,0xbd800000,0xbd800000,0xbd800000,0xbd800000,0xbd800000,
0xbd35bd35,0xbd0ebd55,0xbcc4bd6d,0xbc48bd7b,0xbd800000,0xbd7bbc48,0xbd6dbcc4,0xbd55bd0e,0x3d35bd35,0x3d55bd0e,0x3d6dbcc4,0x3d7bbc48,0x8000bd80,0x3c48bd7b,0x3cc4bd6d,0x3d0ebd55,
0x3d353d35,0x3d0e3d55,0x3cc43d6d,0x3c483d7b,0x3d800000,0x3d7b3c48,0x3d6d3cc4,0x3d553d0e,0xbd353d35,0xbd553d0e,0xbd6d3cc4,0xbd7b3c48,0x80003d80,0xbc483d7b,0xbcc43d6d,0xbd0e3d55,
0x3d800000,0x3d6d3cc4,0x3d353d35,0x3cc43d6d,0x80003d80,0xbcc43d6d,0xbd353d35,0xbd6d3cc4,0xbd800000,0xbd6dbcc4,0xbd35bd35,0xbcc4bd6d,0x8000bd80,0x3cc4bd6d,0x3d35bd35,0x3d6dbcc4,
0x3d800000,0x3d6d3cc4,0x3d353d35,0x3cc43d6d,0x80003d80,0xbcc43d6d,0xbd353d35,0xbd6d3cc4,0xbd800000,0xbd6dbcc4,0xbd35bd35,0xbcc4bd6d,0x8000bd80,0x3cc4bd6d,0x3d35bd35,0x3d6dbcc4,
0xbd35bd35,0xbc48bd7b,0x3cc4bd6d,0x3d55bd0e,0x80003d80,0xbd0e3d55,0xbd6d3cc4,0xbd7bbc48,0x3d35bd35,0x3d7bbc48,0x3d6d3cc4,0x3d0e3d55,0xbd800000,0xbd55bd0e,0xbcc4bd6d,0x3c48bd7b,
0x3d353d35,0x3c483d7b,0xbcc43d6d,0xbd553d0e,0x8000bd80,0x3d0ebd55,0x3d6dbcc4,0x3d7b3c48,0xbd353d35,0xbd7b3c48,0xbd6dbcc4,0xbd0ebd55,0x3d800000,0x3d553d0e,0x3cc43d6d,0xbc483d7b,
0xbd800000,0xbd35bd35,0x8000bd80,0x3d35bd35,0x3d800000,0x3d353d35,0x80003d80,0xbd353d35,0xbd800000,0xbd35bd35,0x8000bd80,0x3d35bd35,0x3d800000,0x3d353d35,0x80003d80,0xbd353d35,
0xbd800000,0xbd35bd35,0x8000bd80,0x3d35bd35,0x3d800000,0x3d353d35,0x80003d80,0xbd353d35,0xbd800000,0xbd35bd35,0x8000bd80,0x3d35bd35,0x3d800000,0x3d353d35,0x80003d80,0xbd353d35,
0xbd35bd35,0x3c48bd7b,0x3d6dbcc4,0x3d553d0e,0x3d800000,0x3d0e3d55,0xbcc43d6d,0xbd7b3c48,0x3d35bd35,0x3d7b3c48,0x3cc43d6d,0xbd0e3d55,0x80003d80,0xbd553d0e,0xbd6dbcc4,0xbc48bd7b,
0x3d353d35,0xbc483d7b,0xbd6d3cc4,0xbd55bd0e,0xbd800000,0xbd0ebd55,0x3cc4bd6d,0x3d7bbc48,0xbd353d35,0xbd7bbc48,0xbcc4bd6d,0x3d0ebd55,0x8000bd80,0x3d55bd0e,0x3d6d3cc4,0x3c483d7b,
0x3d800000,0x3cc43d6d,0xbd353d35,0xbd6dbcc4,0x8000bd80,0x3d6dbcc4,0x3d353d35,0xbcc43d6d,0xbd800000,0xbcc4bd6d,0x3d35bd35,0x3d6d3cc4,0x80003d80,0xbd6d3cc4,0xbd35bd35,0x3cc4bd6d,
0x3d800000,0x3cc43d6d,0xbd353d35,0xbd6dbcc4,0x8000bd80,0x3d6dbcc4,0x3d353d35,0xbcc43d6d,0xbd800000,0xbcc4bd6d,0x3d35bd35,0x3d6d3cc4,0x80003d80,0xbd6d3cc4,0xbd35bd35,0x3cc4bd6d,
0xbd35bd35,0x3d0ebd55,0x3d6d3cc4,0xbc483d7b,0x8000bd80,0x3d7bbc48,0x3cc43d6d,0xbd553d0e,0x3d35bd35,0x3d553d0e,0xbcc43d6d,0xbd7bbc48,0x3d800000,0x3c483d7b,0xbd6d3cc4,0xbd0ebd55,
0x3d353d35,0xbd0e3d55,0xbd6dbcc4,0x3c48bd7b,0x80003d80,0xbd7b3c48,0xbcc4bd6d,0x3d55bd0e,0xbd353d35,0xbd55bd0e,0x3cc4bd6d,0x3d7b3c48,0xbd800000,0xbc48bd7b,0x3d6dbcc4,0x3d0e3d55,
0x3d80,0xbd800000,0xbd80,0x3d800000,0x3d80,0xbd800000,0xbd80,0x3d800000,0x3d80,0xbd800000,0xbd80,0x3d800000,0x3d80,0xbd800000,0xbd80,0x3d800000,
0x3d80,0xbd800000,0xbd80,0x3d800000,0x3d80,0xbd800000,0xbd80,0x3d800000,0x3d80,0xbd800000,0xbd80,0x3d800000,0x3d80,0xbd800000,0xbd80,0x3d800000,
0xbd353d35,0xbd0ebd55,0x3d6dbcc4,0x3c483d7b,0x3d80,0xbd7bbc48,0x3cc4bd6d,0x3d553d0e,0xbd35bd35,0x3d55bd0e,0x3cc43d6d,0xbd7b3c48,0xbd800000,0x3c48bd7b,0x3d6d3cc4,0xbd0e3d55,
0x3d35bd35,0x3d0e3d55,0xbd6d3cc4,0xbc48bd7b,0xbd80,0x3d7b3c48,0xbcc43d6d,0xbd55bd0e,0x3d353d35,0xbd553d0e,0xbcc4bd6d,0x3d7bbc48,0x3d800000,0xbc483d7b,0xbd6dbcc4,0x3d0ebd55,
0xbd80,0x3d6d3cc4,0xbd353d35,0xbcc4bd6d,0x3d800000,0xbcc43d6d,0xbd35bd35,0x3d6dbcc4,0x3d80,0xbd6dbcc4,0x3d35bd35,0x3cc43d6d,0xbd800000,0x3cc4bd6d,0x3d353d35,0xbd6d3cc4,
0xbd80,0x3d6d3cc4,0xbd353d35,0xbcc4bd6d,0x3d800000,0xbcc43d6d,0xbd35bd35,0x3d6dbcc4,0x3d80,0xbd6dbcc4,0x3d35bd35,0x3cc43d6d,0xbd800000,0x3cc4bd6d,0x3d353d35,0xbd6d3cc4,
0xbd353d35,0xbc48bd7b,0x3d6d3cc4,0xbd553d0e,0x3d800000,0xbd0e3d55,0xbcc4bd6d,0x3d7b3c48,0xbd35bd35,0x3d7bbc48,0xbcc43d6d,0xbd0ebd55,0x3d80,0xbd55bd0e,0x3d6dbcc4,0xbc483d7b,
0x3d35bd35,0x3c483d7b,0xbd6dbcc4,0x3d55bd0e,0xbd800000,0x3d0ebd55,0x3cc43d6d,0xbd7bbc48,0x3d353d35,0xbd7b3c48,0x3cc4bd6d,0x3d0e3d55,0xbd80,0x3d553d0e,0xbd6d3cc4,0x3c48bd7b,
0x3d80,0xbd35bd35,0x3d800000,0xbd353d35,0xbd80,0x3d353d35,0xbd800000,0x3d35bd35,0x3d80,0xbd35bd35,0x3d800000,0xbd353d35,0xbd80,0x3d353d35,0xbd800000,0x3d35bd35,
0x3d80,0xbd35bd35,0x3d800000,0xbd353d35,0xbd80,0x3d353d35,0xbd800000,0x3d35bd35,0x3d80,0xbd35bd35,0x3d800000,0xbd353d35,0xbd80,0x3d353d35,0xbd800000,0x3d35bd35,
0xbd353d35,0x3c48bd7b,0x3cc43d6d,0xbd55bd0e,0xbd80,0x3d0e3d55,0xbd6dbcc4,0x3d7bbc48,0xbd35bd35,0x3d7b3c48,0xbd6d3cc4,0x3d0ebd55,0x3d800000,0xbd553d0e,0x3cc4bd6d,0x3c483d7b,
0x3d35bd35,0xbc483d7b,0xbcc4bd6d,0x3d553d0e,0x3d80,0xbd0ebd55,0x3d6d3cc4,0xbd7b3c48,0x3d353d35,0xbd7bbc48,0x3d6dbcc4,0xbd0e3d55,0xbd800000,0x3d55bd0e,0xbcc43d6d,0xbc48bd7b,
0xbd80,0x3cc43d6d,0xbd35bd35,0x3d6d3cc4,0xbd800000,0x3d6dbcc4,0xbd353d35,0x3cc4bd6d,0x3d80,0xbcc4bd6d,0x3d353d35,0xbd6dbcc4,0x3d800000,0xbd6d3cc4,0x3d35bd35,0xbcc43d6d,
0xbd80,0x3cc43d6d,0xbd35bd35,0x3d6d3cc4,0xbd800000,0x3d6dbcc4,0xbd353d35,0x3cc4bd6d,0x3d80,0xbcc4bd6d,0x3d353d35,0xbd6dbcc4,0x3d800000,0xbd6d3cc4,0x3d35bd35,0xbcc43d6d,
0xbd353d35,0x3d0ebd55,0xbcc43d6d,0x3c48bd7b,0xbd800000,0x3d7bbc48,0xbd6d3cc4,0x3d55bd0e,0xbd35bd35,0x3d553d0e,0xbd6dbcc4,0x3d7b3c48,0xbd80,0x3c483d7b,0xbcc4bd6d,0x3d0e3d55,
0x3d35bd35,0xbd0e3d55,0x3cc4bd6d,0xbc483d7b,0x3d800000,0xbd7b3c48,0x3d6dbcc4,0xbd553d0e,0x3d353d35,0xbd55bd0e,0x3d6d3cc4,0xbd7bbc48,0x3d80,0xbc48bd7b,0x3cc43d6d,0xbd0ebd55,
0xbd800000,0x8000bd80,0x3d800000,0x80003d80,0xbd800000,0x8000bd80,0x3d800000,0x80003d80,0xbd800000,0x8000bd80,0x3d800000,0x80003d80,0xbd800000,0x8000bd80,0x3d800000,0x80003d80,
0xbd800000,0x8000bd80,0x3d800000,0x80003d80,0xbd800000,0x8000bd80,0x3d800000,0x80003d80,0xbd800000,0x8000bd80,0x3d800000,0x80003d80,0xbd800000,0x8000bd80,0x3d800000,0x80003d80,
0xbd35bd35,0x3d55bd0e,0x3cc43d6d,0xbd7b3c48,0xbd800000,0x3c48bd7b,0x3d6d3cc4,0xbd0e3d55,0x3d35bd35,0x3d0e3d55,0xbd6d3cc4,0xbc48bd7b,0x8000bd80,0x3d7b3c48,0xbcc43d6d,0xbd55bd0e,
0x3d353d35,0xbd553d0e,0xbcc4bd6d,0x3d7bbc48,0x3d800000,0xbc483d7b,0xbd6dbcc4,0x3d0ebd55,0xbd353d35,0xbd0ebd55,0x3d6dbcc4,0x3c483d7b,0x80003d80,0xbd7bbc48,0x3cc4bd6d,0x3d553d0e,
0x3d800000,0xbcc43d6d,0xbd35bd35,0x3d6dbcc4,0x80003d80,0xbd6dbcc4,0x3d35bd35,0x3cc43d6d,0xbd800000,0x3cc4bd6d,0x3d353d35,0xbd6d3cc4,0x8000bd80,0x3d6d3cc4,0xbd353d35,0xbcc4bd6d,
0x3d800000,0xbcc43d6d,0xbd35bd35,0x3d6dbcc4,0x80003d80,0xbd6dbcc4,0x3d35bd35,0x3cc43d6d,0xbd800000,0x3cc4bd6d,0x3d353d35,0xbd6d3cc4,0x8000bd80,0x3d6d3cc4,0xbd353d35,0xbcc4bd6d,
0xbd35bd35,0x3d7bbc48,0xbcc43d6d,0xbd0ebd55,0x80003d80,0xbd55bd0e,0x3d6dbcc4,0xbc483d7b,0x3d35bd35,0x3c483d7b,0xbd6dbcc4,0x3d55bd0e,0xbd800000,0x3d0ebd55,0x3cc43d6d,0xbd7bbc48,
0x3d353d35,0xbd7b3c48,0x3cc4bd6d,0x3d0e3d55,0x8000bd80,0x3d553d0e,0xbd6d3cc4,0x3c48bd7b,0xbd353d35,0xbc48bd7b,0x3d6d3cc4,0xbd553d0e,0x3d800000,0xbd0e3d55,0xbcc4bd6d,0x3d7b3c48,
0xbd800000,0x3d35bd35,0x80003d80,0xbd35bd35,0x3d800000,0xbd353d35,0x8000bd80,0x3d353d35,0xbd800000,0x3d35bd35,0x80003d80,0xbd35bd35,0x3d800000,0xbd353d35,0x8000bd80,0x3d353d35,
0xbd800000,0x3d35bd35,0x80003d80,0xbd35bd35,0x3d800000,0xbd353d35,0x8000bd80,0x3d353d35,0xbd800000,0x3d35bd35,0x80003d80,0xbd35bd35,0x3d800000,0xbd353d35,0x8000bd80,0x3d353d35,
0xbd35bd35,0x3d7b3c48,0xbd6d3cc4,0x3d0ebd55,0x3d800000,0xbd553d0e,0x3cc4bd6d,0x3c483d7b,0x3d35bd35,0xbc483d7b,0xbcc4bd6d,0x3d553d0e,0x80003d80,0xbd0ebd55,0x3d6d3cc4,0xbd7b3c48,
0x3d353d35,0xbd7bbc48,0x3d6dbcc4,0xbd0e3d55,0xbd800000,0x3d55bd0e,0xbcc43d6d,0xbc48bd7b,0xbd353d35,0x3c48bd7b,0x3cc43d6d,0xbd55bd0e,0x8000bd80,0x3d0e3d55,0xbd6dbcc4,0x3d7bbc48,
0x3d800000,0xbd6d3cc4,0x3d35bd35,0xbcc43d6d,0x8000bd80,0x3cc43d6d,0xbd35bd35,0x3d6d3cc4,0xbd800000,0x3d6dbcc4,0xbd353d35,0x3cc4bd6d,0x80003d80,0xbcc4bd6d,0x3d353d35,0xbd6dbcc4,
0x3d800000,0xbd6d3cc4,0x3d35bd35,0xbcc43d6d,0x8000bd80,0x3cc43d6d,0xbd35bd35,0x3d6d3cc4,0xbd800000,0x3d6dbcc4,0xbd353d35,0x3cc4bd6d,0x80003d80,0xbcc4bd6d,0x3d353d35,0xbd6dbcc4,
0xbd35bd35,0x3d553d0e,0xbd6dbcc4,0x3d7b3c48,0x8000bd80,0x3c483d7b,0xbcc4bd6d,0x3d0e3d55,0x3d35bd35,0xbd0e3d55,0x3cc4bd6d,0xbc483d7b,0x3d800000,0xbd7b3c48,0x3d6dbcc4,0xbd553d0e,
0x3d353d35,0xbd55bd0e,0x3d6d3cc4,0xbd7bbc48,0x80003d80,0xbc48bd7b,0x3cc43d6d,0xbd0ebd55,0xbd353d35,0x3d0ebd55,0xbcc43d6d,0x3c48bd7b,0xbd800000,0x3d7bbc48,0xbd6d3cc4,0x3d55bd0e,
0x3d80,0xbd80,0x3d80,0xbd80,0x3d80,0xbd80,0x3d80,0xbd80,0x3d80,0xbd80,0x3d80,0xbd80,0x3d80,0xbd80,0x3d80,0xbd80,
0x3d80,0xbd80,0x3d80,0xbd80,0x3d80,0xbd80,0x3d80,0xbd80,0x3d80,0xbd80,0x3d80,0xbd80,0x3d80,0xbd80,0x3d80,0xbd80,
0xbd353d35,0x3d55bd0e,0xbd6d3cc4,0x3d7bbc48,0x3d80,0x3c48bd7b,0xbcc43d6d,0x3d0ebd55,0xbd35bd35,0x3d0e3d55,0xbcc4bd6d,0x3c483d7b,0xbd800000,0x3d7b3c48,0xbd6dbcc4,0x3d553d0e,
0x3d35bd35,0xbd553d0e,0x3d6dbcc4,0xbd7b3c48,0xbd80,0xbc483d7b,0x3cc4bd6d,0xbd0e3d55,0x3d353d35,0xbd0ebd55,0x3cc43d6d,0xbc48bd7b,0x3d800000,0xbd7bbc48,0x3d6d3cc4,0xbd55bd0e,
0xbd80,0xbcc43d6d,0x3d35bd35,0xbd6d3cc4,0x3d800000,0xbd6dbcc4,0x3d353d35,0xbcc4bd6d,0x3d80,0x3cc4bd6d,0xbd353d35,0x3d6dbcc4,0xbd800000,0x3d6d3cc4,0xbd35bd35,0x3cc43d6d,
0xbd80,0xbcc43d6d,0x3d35bd35,0xbd6d3cc4,0x3d800000,0xbd6dbcc4,0x3d353d35,0xbcc4bd6d,0x3d80,0x3cc4bd6d,0xbd353d35,0x3d6dbcc4,0xbd800000,0x3d6d3cc4,0xbd35bd35,0x3cc43d6d,
0xbd353d35,0x3d7bbc48,0xbd6dbcc4,0x3d0e3d55,0x3d800000,0xbd55bd0e,0x3cc43d6d,0x3c48bd7b,0xbd35bd35,0x3c483d7b,0x3cc4bd6d,0xbd553d0e,0x3d80,0x3d0ebd55,0xbd6d3cc4,0x3d7b3c48,
0x3d35bd35,0xbd7b3c48,0x3d6d3cc4,0xbd0ebd55,0xbd800000,0x3d553d0e,0xbcc4bd6d,0xbc483d7b,0x3d353d35,0xbc48bd7b,0xbcc43d6d,0x3d55bd0e,0xbd80,0xbd0e3d55,0x3d6dbcc4,0xbd7bbc48,
0x3d80,0x3d35bd35,0xbd800000,0x3d353d35,0xbd80,0xbd353d35,0x3d800000,0xbd35bd35,0x3d80,0x3d35bd35,0xbd800000,0x3d353d35,0xbd80,0xbd353d35,0x3d800000,0xbd35bd35,
0x3d80,0x3d35bd35,0xbd800000,0x3d353d35,0xbd80,0xbd353d35,0x3d800000,0xbd35bd35,0x3d80,0x3d35bd35,0xbd800000,0x3d353d35,0xbd80,0xbd353d35,0x3d800000,0xbd35bd35,
0xbd353d35,0x3d7b3c48,0xbcc4bd6d,0xbd0e3d55,0xbd80,0xbd553d0e,0x3d6d3cc4,0xbc48bd7b,0xbd35bd35,0xbc483d7b,0x3d6dbcc4,0xbd55bd0e,0x3d800000,0xbd0ebd55,0xbcc43d6d,0x3d7bbc48,
0x3d35bd35,0xbd7bbc48,0x3cc43d6d,0x3d0ebd55,0x3d80,0x3d55bd0e,0xbd6dbcc4,0x3c483d7b,0x3d353d35,0x3c48bd7b,0xbd6d3cc4,0x3d553d0e,0xbd800000,0x3d0e3d55,0x3cc4bd6d,0xbd7b3c48,
0xbd80,0xbd6d3cc4,0x3d353d35,0x3cc4bd6d,0xbd800000,0x3cc43d6d,0x3d35bd35,0xbd6dbcc4,0x3d80,0x3d6dbcc4,0xbd35bd35,0xbcc43d6d,0x3d800000,0xbcc4bd6d,0xbd353d35,0x3d6d3cc4,
0xbd80,0xbd6d3cc4,0x3d353d35,0x3cc4bd6d,0xbd800000,0x3cc43d6d,0x3d35bd35,0xbd6dbcc4,0x3d80,0x3d6dbcc4,0xbd35bd35,0xbcc43d6d,0x3d800000,0xbcc4bd6d,0xbd353d35,0x3d6d3cc4,
0xbd353d35,0x3d553d0e,0x3cc4bd6d,0xbd7bbc48,0xbd800000,0x3c483d7b,0x3d6dbcc4,0xbd0ebd55,0xbd35bd35,0xbd0e3d55,0x3d6d3cc4,0x3c48bd7b,0xbd80,0xbd7b3c48,0x3cc43d6d,0x3d55bd0e,
0x3d35bd35,0xbd55bd0e,0xbcc43d6d,0x3d7b3c48,0x3d800000,0xbc48bd7b,0xbd6d3cc4,0x3d0e3d55,0x3d353d35,0x3d0ebd55,0xbd6dbcc4,0xbc483d7b,0x3d80,0x3d7bbc48,0xbcc4bd6d,0xbd553d0e,
0xbd800000,0x3d800000,0xbd800000,0x3d800000,0xbd800000,0x3d800000,0xbd800000,0x3d800000,0xbd800000,0x3d800000,0xbd800000,0x3d800000,0xbd800000,0x3d800000,0xbd800000,0x3d800000,
0xbd800000,0x3d800000,0xbd800000,0x3d800000,0xbd800000,0x3d800000,0xbd800000,0x3d800000,0xbd800000,0x3d800000,0xbd800000,0x3d800000,0xbd800000,0x3d800000,0xbd800000,0x3d800000,
0xbd35bd35,0x3d0e3d55,0xbcc4bd6d,0x3c483d7b,0xbd800000,0x3d7b3c48,0xbd6dbcc4,0x3d553d0e,0x3d35bd35,0xbd553d0e,0x3d6dbcc4,0xbd7b3c48,0x8000bd80,0xbc483d7b,0x3cc4bd6d,0xbd0e3d55,
0x3d353d35,0xbd0ebd55,0x3cc43d6d,0xbc48bd7b,0x3d800000,0xbd7bbc48,0x3d6d3cc4,0xbd55bd0e,0xbd353d35,0x3d55bd0e,0xbd6d3cc4,0x3d7bbc48,0x80003d80,0x3c48bd7b,0xbcc43d6d,0x3d0ebd55,
0x3d800000,0xbd6dbcc4,0x3d353d35,0xbcc4bd6d,0x80003d80,0x3cc4bd6d,0xbd353d35,0x3d6dbcc4,0xbd800000,0x3d6d3cc4,0xbd35bd35,0x3cc43d6d,0x8000bd80,0xbcc43d6d,0x3d35bd35,0xbd6d3cc4,
0x3d800000,0xbd6dbcc4,0x3d353d35,0xbcc4bd6d,0x80003d80,0x3cc4bd6d,0xbd353d35,0x3d6dbcc4,0xbd800000,0x3d6d3cc4,0xbd35bd35,0x3cc43d6d,0x8000bd80,0xbcc43d6d,0x3d35bd35,0xbd6d3cc4,
0xbd35bd35,0x3c483d7b,0x3cc4bd6d,0xbd553d0e,0x80003d80,0x3d0ebd55,0xbd6d3cc4,0x3d7b3c48,0x3d35bd35,0xbd7b3c48,0x3d6d3cc4,0xbd0ebd55,0xbd800000,0x3d553d0e,0xbcc4bd6d,0xbc483d7b,
0x3d353d35,0xbc48bd7b,0xbcc43d6d,0x3d55bd0e,0x8000bd80,0xbd0e3d55,0x3d6dbcc4,0xbd7bbc48,0xbd353d35,0x3d7bbc48,0xbd6dbcc4,0x3d0e3d55,0x3d800000,0xbd55bd0e,0x3cc43d6d,0x3c48bd7b,
0xbd800000,0x3d353d35,0x8000bd80,0xbd353d35,0x3d800000,0xbd35bd35,0x80003d80,0x3d35bd35,0xbd800000,0x3d353d35,0x8000bd80,0xbd353d35,0x3d800000,0xbd35bd35,0x80003d80,0x3d35bd35,
0xbd800000,0x3d353d35,0x8000bd80,0xbd353d35,0x3d800000,0xbd35bd35,0x80003d80,0x3d35bd35,0xbd800000,0x3d353d35,0x8000bd80,0xbd353d35,0x3d800000,0xbd35bd35,0x80003d80,0x3d35bd35,
0xbd35bd35,0xbc483d7b,0x3d6dbcc4,0xbd55bd0e,0x3d800000,0xbd0ebd55,0xbcc43d6d,0x3d7bbc48,0x3d35bd35,0xbd7bbc48,0x3cc43d6d,0x3d0ebd55,0x80003d80,0x3d55bd0e,0xbd6dbcc4,0x3c483d7b,
0x3d353d35,0x3c48bd7b,0xbd6d3cc4,0x3d553d0e,0xbd800000,0x3d0e3d55,0x3cc4bd6d,0xbd7b3c48,0xbd353d35,0x3d7b3c48,0xbcc4bd6d,0xbd0e3d55,0x8000bd80,0xbd553d0e,0x3d6d3cc4,0xbc48bd7b,
0x3d800000,0xbcc4bd6d,0xbd353d35,0x3d6d3cc4,0x8000bd80,0xbd6d3cc4,0x3d353d35,0x3cc4bd6d,0xbd800000,0x3cc43d6d,0x3d35bd35,0xbd6dbcc4,0x80003d80,0x3d6dbcc4,0xbd35bd35,0xbcc43d6d,
0x3d800000,0xbcc4bd6d,0xbd353d35,0x3d6d3cc4,0x8000bd80,0xbd6d3cc4,0x3d353d35,0x3cc4bd6d,0xbd800000,0x3cc43d6d,0x3d35bd35,0xbd6dbcc4,0x80003d80,0x3d6dbcc4,0xbd35bd35,0xbcc43d6d,
0xbd35bd35,0xbd0e3d55,0x3d6d3cc4,0x3c48bd7b,0x8000bd80,0xbd7b3c48,0x3cc43d6d,0x3d55bd0e,0x3d35bd35,0xbd55bd0e,0xbcc43d6d,0x3d7b3c48,0x3d800000,0xbc48bd7b,0xbd6d3cc4,0x3d0e3d55,
0x3d353d35,0x3d0ebd55,0xbd6dbcc4,0xbc483d7b,0x80003d80,0x3d7bbc48,0xbcc4bd6d,0xbd553d0e,0xbd353d35,0x3d553d0e,0x3cc4bd6d,0xbd7bbc48,0xbd800000,0x3c483d7b,0x3d6dbcc4,0xbd0ebd55,
0x3d80,0x3d800000,0xbd80,0xbd800000,0x3d80,0x3d800000,0xbd80,0xbd800000,0x3d80,0x3d800000,0xbd80,0xbd800000,0x3d80,0x3d800000,0xbd80,0xbd800000,
0x3d80,0x3d800000,0xbd80,0xbd800000,0x3d80,0x3d800000,0xbd80,0xbd800000,0x3d80,0x3d800000,0xbd80,0xbd800000,0x3d80,0x3d800000,0xbd80,0xbd800000,
0xbd353d35,0x3d0e3d55,0x3d6dbcc4,0xbc48bd7b,0x3d80,0x3d7b3c48,0x3cc4bd6d,0xbd55bd0e,0xbd35bd35,0xbd553d0e,0x3cc43d6d,0x3d7bbc48,0xbd800000,0xbc483d7b,0x3d6d3cc4,0x3d0ebd55,
0x3d35bd35,0xbd0ebd55,0xbd6d3cc4,0x3c483d7b,0xbd80,0xbd7bbc48,0xbcc43d6d,0x3d553d0e,0x3d353d35,0x3d55bd0e,0xbcc4bd6d,0xbd7b3c48,0x3d800000,0x3c48bd7b,0xbd6dbcc4,0xbd0e3d55,
0xbd80,0xbd6dbcc4,0xbd353d35,0x3cc43d6d,0x3d800000,0x3cc4bd6d,0xbd35bd35,0xbd6d3cc4,0x3d80,0x3d6d3cc4,0x3d35bd35,0xbcc4bd6d,0xbd800000,0xbcc43d6d,0x3d353d35,0x3d6dbcc4,
0xbd80,0xbd6dbcc4,0xbd353d35,0x3cc43d6d,0x3d800000,0x3cc4bd6d,0xbd35bd35,0xbd6d3cc4,0x3d80,0x3d6d3cc4,0x3d35bd35,0xbcc4bd6d,0xbd800000,0xbcc43d6d,0x3d353d35,0x3d6dbcc4,
0xbd353d35,0x3c483d7b,0x3d6d3cc4,0x3d55bd0e,0x3d800000,0x3d0ebd55,0xbcc4bd6d,0xbd7bbc48,0xbd35bd35,0xbd7b3c48,0xbcc43d6d,0x3d0e3d55,0x3d80,0x3d553d0e,0x3d6dbcc4,0x3c48bd7b,
0x3d35bd35,0xbc48bd7b,0xbd6dbcc4,0xbd553d0e,0xbd800000,0xbd0e3d55,0x3cc43d6d,0x3d7b3c48,0x3d353d35,0x3d7bbc48,0x3cc4bd6d,0xbd0ebd55,0xbd80,0xbd55bd0e,0xbd6d3cc4,0xbc483d7b,
0x3d80,0x3d353d35,0x3d800000,0x3d35bd35,0xbd80,0xbd35bd35,0xbd800000,0xbd353d35,0x3d80,0x3d353d35,0x3d800000,0x3d35bd35,0xbd80,0xbd35bd35,0xbd800000,0xbd353d35,
0x3d80,0x3d353d35,0x3d800000,0x3d35bd35,0xbd80,0xbd35bd35,0xbd800000,0xbd353d35,0x3d80,0x3d353d35,0x3d800000,0x3d35bd35,0xbd80,0xbd35bd35,0xbd800000,0xbd353d35,
0xbd353d35,0xbc483d7b,0x3cc43d6d,0x3d553d0e,0xbd80,0xbd0ebd55,0xbd6dbcc4,0xbd7b3c48,0xbd35bd35,0xbd7bbc48,0xbd6d3cc4,0xbd0e3d55,0x3d800000,0x3d55bd0e,0x3cc4bd6d,0xbc48bd7b,
0x3d35bd35,0x3c48bd7b,0xbcc4bd6d,0xbd55bd0e,0x3d80,0x3d0e3d55,0x3d6d3cc4,0x3d7bbc48,0x3d353d35,0x3d7b3c48,0x3d6dbcc4,0x3d0ebd55,0xbd800000,0xbd553d0e,0xbcc43d6d,0x3c483d7b,
0xbd80,0xbcc4bd6d,0xbd35bd35,0xbd6dbcc4,0xbd800000,0xbd6d3cc4,0xbd353d35,0xbcc43d6d,0x3d80,0x3cc43d6d,0x3d353d35,0x3d6d3cc4,0x3d800000,0x3d6dbcc4,0x3d35bd35,0x3cc4bd6d,
0xbd80,0xbcc4bd6d,0xbd35bd35,0xbd6dbcc4,0xbd800000,0xbd6d3cc4,0xbd353d35,0xbcc43d6d,0x3d80,0x3cc43d6d,0x3d353d35,0x3d6d3cc4,0x3d800000,0x3d6dbcc4,0x3d35bd35,0x3cc4bd6d,
0xbd353d35,0xbd0e3d55,0xbcc43d6d,0xbc483d7b,0xbd800000,0xbd7b3c48,0xbd6d3cc4,0xbd553d0e,0xbd35bd35,0xbd55bd0e,0xbd6dbcc4,0xbd7bbc48,0xbd80,0xbc48bd7b,0xbcc4bd6d,0xbd0ebd55,
0x3d35bd35,0x3d0ebd55,0x3cc4bd6d,0x3c48bd7b,0x3d800000,0x3d7bbc48,0x3d6dbcc4,0x3d55bd0e,0x3d353d35,0x3d553d0e,0x3d6d3cc4,0x3d7b3c48,0x3d80,0x3c483d7b,0x3cc43d6d,0x3d0e3d55,
0xbd800000,0x80003d80,0x3d800000,0x8000bd80,0xbd800000,0x80003d80,0x3d800000,0x8000bd80,0xbd800000,0x80003d80,0x3d800000,0x8000bd80,0xbd800000,0x80003d80,0x3d800000,0x8000bd80,
0xbd800000,0x80003d80,0x3d800000,0x8000bd80,0xbd800000,0x80003d80,0x3d800000,0x8000bd80,0xbd800000,0x80003d80,0x3d800000,0x8000bd80,0xbd800000,0x80003d80,0x3d800000,0x8000bd80,
0xbd35bd35,0xbd553d0e,0x3cc43d6d,0x3d7bbc48,0xbd800000,0xbc483d7b,0x3d6d3cc4,0x3d0ebd55,0x3d35bd35,0xbd0ebd55,0xbd6d3cc4,0x3c483d7b,0x8000bd80,0xbd7bbc48,0xbcc43d6d,0x3d553d0e,
0x3d353d35,0x3d55bd0e,0xbcc4bd6d,0xbd7b3c48,0x3d800000,0x3c48bd7b,0xbd6dbcc4,0xbd0e3d55,0xbd353d35,0x3d0e3d55,0x3d6dbcc4,0xbc48bd7b,0x80003d80,0x3d7b3c48,0x3cc4bd6d,0xbd55bd0e,
0x3d800000,0x3cc4bd6d,0xbd35bd35,0xbd6d3cc4,0x80003d80,0x3d6d3cc4,0x3d35bd35,0xbcc4bd6d,0xbd800000,0xbcc43d6d,0x3d353d35,0x3d6dbcc4,0x8000bd80,0xbd6dbcc4,0xbd353d35,0x3cc43d6d,
0x3d800000,0x3cc4bd6d,0xbd35bd35,0xbd6d3cc4,0x80003d80,0x3d6d3cc4,0x3d35bd35,0xbcc4bd6d,0xbd800000,0xbcc43d6d,0x3d353d35,0x3d6dbcc4,0x8000bd80,0xbd6dbcc4,0xbd353d35,0x3cc43d6d,
0xbd35bd35,0xbd7b3c48,0xbcc43d6d,0x3d0e3d55,0x80003d80,0x3d553d0e,0x3d6dbcc4,0x3c48bd7b,0x3d35bd35,0xbc48bd7b,0xbd6dbcc4,0xbd553d0e,0xbd800000,0xbd0e3d55,0x3cc43d6d,0x3d7b3c48,
0x3d353d35,0x3d7bbc48,0x3cc4bd6d,0xbd0ebd55,0x8000bd80,0xbd55bd0e,0xbd6d3cc4,0xbc483d7b,0xbd353d35,0x3c483d7b,0x3d6d3cc4,0x3d55bd0e,0x3d800000,0x3d0ebd55,0xbcc4bd6d,0xbd7bbc48,
0xbd800000,0xbd353d35,0x80003d80,0x3d353d35,0x3d800000,0x3d35bd35,0x8000bd80,0xbd35bd35,0xbd800000,0xbd353d35,0x80003d80,0x3d353d35,0x3d800000,0x3d35bd35,0x8000bd80,0xbd35bd35,
0xbd800000,0xbd353d35,0x80003d80,0x3d353d35,0x3d800000,0x3d35bd35,0x8000bd80,0xbd35bd35,0xbd800000,0xbd353d35,0x80003d80,0x3d353d35,0x3d800000,0x3d35bd35,0x8000bd80,0xbd35bd35,
0xbd35bd35,0xbd7bbc48,0xbd6d3cc4,0xbd0e3d55,0x3d800000,0x3d55bd0e,0x3cc4bd6d,0xbc48bd7b,0x3d35bd35,0x3c48bd7b,0xbcc4bd6d,0xbd55bd0e,0x80003d80,0x3d0e3d55,0x3d6d3cc4,0x3d7bbc48,
0x3d353d35,0x3d7b3c48,0x3d6dbcc4,0x3d0ebd55,0xbd800000,0xbd553d0e,0xbcc43d6d,0x3c483d7b,0xbd353d35,0xbc483d7b,0x3cc43d6d,0x3d553d0e,0x8000bd80,0xbd0ebd55,0xbd6dbcc4,0xbd7b3c48,
0x3d800000,0x3d6dbcc4,0x3d35bd35,0x3cc4bd6d,0x8000bd80,0xbcc4bd6d,0xbd35bd35,0xbd6dbcc4,0xbd800000,0xbd6d3cc4,0xbd353d35,0xbcc43d6d,0x80003d80,0x3cc43d6d,0x3d353d35,0x3d6d3cc4,
0x3d800000,0x3d6dbcc4,0x3d35bd35,0x3cc4bd6d,0x8000bd80,0xbcc4bd6d,0xbd35bd35,0xbd6dbcc4,0xbd800000,0xbd6d3cc4,0xbd353d35,0xbcc43d6d,0x80003d80,0x3cc43d6d,0x3d353d35,0x3d6d3cc4,
0xbd35bd35,0xbd55bd0e,0xbd6dbcc4,0xbd7bbc48,0x8000bd80,0xbc48bd7b,0xbcc4bd6d,0xbd0ebd55,0x3d35bd35,0x3d0ebd55,0x3cc4bd6d,0x3c48bd7b,0x3d800000,0x3d7bbc48,0x3d6dbcc4,0x3d55bd0e,
0x3d353d35,0x3d553d0e,0x3d6d3cc4,0x3d7b3c48,0x80003d80,0x3c483d7b,0x3cc43d6d,0x3d0e3d55,0xbd353d35,0xbd0e3d55,0xbcc43d6d,0xbc483d7b,0xbd800000,0xbd7b3c48,0xbd6d3cc4,0xbd553d0e,
0x3d80,0xbb493d80,0xbbc93d7f,0xbc163d7d,0xbc483d7b,0xbc793d78,0xbc953d75,0xbcac3d71,0xbcc43d6d,0xbcdb3d67,0xbcf13d62,0xbd043d5c,0xbd0e3d55,0xbd183d4e,0xbd223d46,0xbd2c3d3e,
0xbd353d35,0xbd3e3d2c,0xbd463d22,0xbd4e3d18,0xbd553d0e,0xbd5c3d04,0xbd623cf1,0xbd673cdb,0xbd6d3cc4,0xbd713cac,0xbd753c95,0xbd783c79,0xbd7b3c48,0xbd7d3c16,0xbd7f3bc9,0xbd803b49,
0xbd553d0e,0xbd713cac,0xbd7f3bc9,0xbd7dbc16,0x3d80,0xbc793d78,0xbcf13d62,0xbd2c3d3e,0xbc48bd7b,0x3b49bd80,0x3c95bd75,0x3d04bd5c,0xbd6dbcc4,0xbd4ebd18,0xbd22bd46,0xbcdbbd67,
0x3d7b3c48,0x3d673cdb,0x3d463d22,0x3d183d4e,0x3d35bd35,0x3d5cbd04,0x3d75bc95,0x3d80bb49,0xbd0e3d55,0xbd3e3d2c,0xbd623cf1,0xbd783c79,0x3cc43d6d,0x3c163d7d,0xbbc93d7f,0xbcac3d71,
0x3cc4bd6d,0x3d3ebd2c,0x3d75bc95,0x3d7d3c16,0x3d553d0e,0x3d043d5c,0x3bc93d7f,0xbcac3d71,0x3d80,0xbcdb3d67,0xbd463d22,0xbd783c79,0xbd7bbc48,0xbd4ebd18,0xbcf1bd62,0xbb49bd80,
0x3d6dbcc4,0x3d803b49,0x3d623cf1,0x3d183d4e,0x3c483d7b,0xbc793d78,0xbd223d46,0xbd673cdb,0xbd353d35,0xbd713cac,0xbd7fbbc9,0xbd5cbd04,0xbd0ebd55,0xbc16bd7d,0x3c95bd75,0x3d2cbd3e,
0xbd7b3c48,0xbd67bcdb,0xbcf1bd62,0x3c16bd7d,0x3d6d3cc4,0x3d043d5c,0xbbc93d7f,0xbd2c3d3e,0xbd0ebd55,0x3b49bd80,0x3d22bd46,0x3d78bc79,0x3d80,0xbd183d4e,0xbd753c95,0xbd71bcac,
0x3d553d0e,0x3cac3d71,0xbc953d75,0xbd4e3d18,0xbcc4bd6d,0x3c79bd78,0x3d46bd22,0x3d80bb49,0xbc483d7b,0xbd3e3d2c,0xbd7f3bc9,0xbd5cbd04,0x3d35bd35,0x3d7dbc16,0x3d623cf1,0x3cdb3d67,
0xbd353d35,0xbd80bb49,0xbd22bd46,0x3c16bd7d,0x3d55bd0e,0x3d783c79,0x3cf13d62,0xbcac3d71,0xbd6d3cc4,0xbd67bcdb,0xbc95bd75,0x3d04bd5c,0x3d7bbc48,0x3d4e3d18,0x3bc93d7f,0xbd2c3d3e,
0x3d80,0xbd3e3d2c,0xbd7fbbc9,0xbd18bd4e,0x3c48bd7b,0x3d5cbd04,0x3d753c95,0x3cdb3d67,0xbcc43d6d,0xbd713cac,0xbd62bcf1,0xbc79bd78,0x3d0ebd55,0x3d7dbc16,0x3d463d22,0x3b493d80,
0xbd7bbc48,0xbcacbd71,0x3d22bd46,0x3d7d3c16,0x3d35bd35,0x3d783c79,0x3c953d75,0xbd2c3d3e,0x3d0ebd55,0x3d803b49,0x3cf13d62,0xbd043d5c,0x3cc43d6d,0xbd183d4e,0xbd7fbbc9,0xbcdbbd67,
0x3d55bd0e,0x3d673cdb,0x3bc93d7f,0xbd4e3d18,0x3d80,0xbd5c3d04,0xbd62bcf1,0xbb49bd80,0x3c483d7b,0xbd3e3d2c,0xbd75bc95,0xbc79bd78,0xbd6dbcc4,0xbc16bd7d,0x3d46bd22,0x3d713cac,
0x3d6dbcc4,0x3d2c3d3e,0xbcf13d62,0xbd7dbc16,0xbc48bd7b,0x3d5cbd04,0x3d463d22,0xbcac3d71,0xbd353d35,0xbd67bcdb,0x3bc9bd7f,0x3d78bc79,0x3d0e3d55,0xbd183d4e,0xbd75bc95,0xbb49bd80,
0x3cc4bd6d,0x3d803b49,0x3c953d75,0xbd4e3d18,0xbd55bd0e,0x3c79bd78,0x3d7fbbc9,0x3cdb3d67,0x3d80,0xbd713cac,0xbd22bd46,0x3d04bd5c,0x3d7b3c48,0x3c163d7d,0xbd623cf1,0xbd3ebd2c,
0xbd55bd0e,0x3cdbbd67,0x3d753c95,0xbc163d7d,0xbcc4bd6d,0x3d5cbd04,0x3d223d46,0xbd2c3d3e,0x3c48bd7b,0x3d803b49,0x3bc93d7f,0xbd783c79,0x3d35bd35,0x3d4e3d18,0xbcf13d62,0xbd71bcac,
0x3d7bbc48,0x3cac3d71,0xbd623cf1,0xbd18bd4e,0x3d6d3cc4,0xbc793d78,0xbd7fbbc9,0xbb49bd80,0x3d0e3d55,0xbd3e3d2c,0xbd46bd22,0x3d04bd5c,0x3d80,0xbd7d3c16,0xbc95bd75,0x3d67bcdb,
0xbd800000,0xbd80bb49,0xbd7fbbc9,0xbd7dbc16,0xbd7bbc48,0xbd78bc79,0xbd75bc95,0xbd71bcac,0xbd6dbcc4,0xbd67bcdb,0xbd62bcf1,0xbd5cbd04,0xbd55bd0e,0xbd4ebd18,0xbd46bd22,0xbd3ebd2c,
0xbd35bd35,0xbd2cbd3e,0xbd22bd46,0xbd18bd4e,0xbd0ebd55,0xbd04bd5c,0xbcf1bd62,0xbcdbbd67,0xbcc4bd6d,0xbcacbd71,0xbc95bd75,0xbc79bd78,0xbc48bd7b,0xbc16bd7d,0xbbc9bd7f,0xbb49bd80,
0xbd0ebd55,0xbcacbd71,0xbbc9bd7f,0x3c16bd7d,0xbd800000,0xbd78bc79,0xbd62bcf1,0xbd3ebd2c,0x3d7bbc48,0x3d803b49,0x3d753c95,0x3d5c3d04,0x3cc4bd6d,0x3d18bd4e,0x3d46bd22,0x3d67bcdb,
0xbc483d7b,0xbcdb3d67,0xbd223d46,0xbd4e3d18,0x3d353d35,0x3d043d5c,0x3c953d75,0x3b493d80,0xbd55bd0e,0xbd2cbd3e,0xbcf1bd62,0xbc79bd78,0xbd6d3cc4,0xbd7d3c16,0xbd7fbbc9,0xbd71bcac,
0x3d6d3cc4,0x3d2c3d3e,0x3c953d75,0xbc163d7d,0xbd0e3d55,0xbd5c3d04,0xbd7f3bc9,0xbd71bcac,0xbd800000,0xbd67bcdb,0xbd22bd46,0xbc79bd78,0x3c48bd7b,0x3d18bd4e,0x3d62bcf1,0x3d80bb49,
0x3cc43d6d,0xbb493d80,0xbcf13d62,0xbd4e3d18,0xbd7b3c48,0xbd78bc79,0xbd46bd22,0xbcdbbd67,0xbd35bd35,0xbcacbd71,0x3bc9bd7f,0x3d04bd5c,0x3d55bd0e,0x3d7dbc16,0x3d753c95,0x3d3e3d2c,
0xbc48bd7b,0x3cdbbd67,0x3d62bcf1,0x3d7d3c16,0xbcc43d6d,0xbd5c3d04,0xbd7fbbc9,0xbd3ebd2c,0x3d55bd0e,0x3d803b49,0x3d463d22,0x3c793d78,0xbd800000,0xbd4ebd18,0xbc95bd75,0x3cacbd71,
0xbd0e3d55,0xbd713cac,0xbd75bc95,0xbd18bd4e,0x3d6dbcc4,0x3d783c79,0x3d223d46,0x3b493d80,0xbd7bbc48,0xbd2cbd3e,0xbbc9bd7f,0x3d04bd5c,0x3d353d35,0x3c163d7d,0xbcf13d62,0xbd673cdb,
0xbd35bd35,0x3b49bd80,0x3d46bd22,0x3d7d3c16,0x3d0e3d55,0xbc793d78,0xbd623cf1,0xbd71bcac,0xbcc4bd6d,0x3cdbbd67,0x3d75bc95,0x3d5c3d04,0x3c483d7b,0xbd183d4e,0xbd7f3bc9,0xbd3ebd2c,
0xbd800000,0xbd2cbd3e,0x3bc9bd7f,0x3d4ebd18,0x3d7b3c48,0x3d043d5c,0xbc953d75,0xbd673cdb,0xbd6dbcc4,0xbcacbd71,0x3cf1bd62,0x3d78bc79,0x3d553d0e,0x3c163d7d,0xbd223d46,0xbd803b49,
0x3c48bd7b,0x3d71bcac,0x3d463d22,0xbc163d7d,0x3d353d35,0xbc793d78,0xbd753c95,0xbd3ebd2c,0x3d553d0e,0xbb493d80,0xbd623cf1,0xbd5cbd04,0xbd6d3cc4,0xbd4ebd18,0x3bc9bd7f,0x3d67bcdb,
0x3d0e3d55,0xbcdb3d67,0xbd7f3bc9,0xbd18bd4e,0xbd800000,0xbd04bd5c,0x3cf1bd62,0x3d80bb49,0xbd7b3c48,0xbd2cbd3e,0x3c95bd75,0x3d78bc79,0x3cc4bd6d,0x3d7dbc16,0x3d223d46,0xbcac3d71,
0x3cc43d6d,0xbd3e3d2c,0xbd62bcf1,0x3c16bd7d,0x3d7bbc48,0x3d043d5c,0xbd223d46,0xbd71bcac,0xbd35bd35,0x3cdbbd67,0x3d7f3bc9,0x3c793d78,0xbd553d0e,0xbd4ebd18,0x3c95bd75,0x3d80bb49,
0x3d6d3cc4,0xbb493d80,0xbd753c95,0xbd18bd4e,0x3d0ebd55,0x3d783c79,0x3bc93d7f,0xbd673cdb,0xbd800000,0xbcacbd71,0x3d46bd22,0x3d5c3d04,0xbc483d7b,0xbd7d3c16,0xbcf1bd62,0x3d2cbd3e,
0x3d0ebd55,0x3d673cdb,0xbc953d75,0xbd7dbc16,0x3d6dbcc4,0x3d043d5c,0xbd463d22,0xbd3ebd2c,0x3d7b3c48,0xbb493d80,0xbd7f3bc9,0xbc79bd78,0x3d353d35,0xbd183d4e,0xbd62bcf1,0x3cacbd71,
0x3c483d7b,0xbd713cac,0xbcf1bd62,0x3d4ebd18,0xbcc43d6d,0xbd78bc79,0x3bc9bd7f,0x3d80bb49,0xbd553d0e,0xbd2cbd3e,0x3d22bd46,0x3d5c3d04,0xbd800000,0xbc16bd7d,0x3d75bc95,0x3cdb3d67,
0x3d80,0xbd80bb49,0x3bc9bd7f,0x3d7d3c16,0xbc483d7b,0xbd78bc79,0x3c95bd75,0x3d713cac,0xbcc43d6d,0xbd67bcdb,0x3cf1bd62,0x3d5c3d04,0xbd0e3d55,0xbd4ebd18,0x3d22bd46,0x3d3e3d2c,
0xbd353d35,0xbd2cbd3e,0x3d46bd22,0x3d183d4e,0xbd553d0e,0xbd04bd5c,0x3d62bcf1,0x3cdb3d67,0xbd6d3cc4,0xbcacbd71,0x3d75bc95,0x3c793d78,0xbd7b3c48,0xbc16bd7d,0x3d7fbbc9,0x3b493d80,
0xbd553d0e,0xbcacbd71,0x3d7fbbc9,0xbc163d7d,0x3d80,0xbd78bc79,0x3cf1bd62,0x3d3e3d2c,0xbc48bd7b,0x3d803b49,0xbc953d75,0xbd5cbd04,0xbd6dbcc4,0x3d18bd4e,0x3d223d46,0xbd673cdb,
0x3d7b3c48,0xbcdb3d67,0xbd46bd22,0x3d4ebd18,0x3d35bd35,0x3d043d5c,0xbd753c95,0xbb49bd80,0xbd0e3d55,0xbd2cbd3e,0x3d62bcf1,0x3c793d78,0x3cc43d6d,0xbd7d3c16,0x3bc9bd7f,0x3d713cac,
0x3cc4bd6d,0x3d2c3d3e,0xbd753c95,0x3c16bd7d,0x3d553d0e,0xbd5c3d04,0xbbc9bd7f,0x3d713cac,0x3d80,0xbd67bcdb,0x3d46bd22,0x3c793d78,0xbd7bbc48,0x3d18bd4e,0x3cf13d62,0xbd803b49,
0x3d6dbcc4,0xbb493d80,0xbd62bcf1,0x3d4ebd18,0x3c483d7b,0xbd78bc79,0x3d22bd46,0x3cdb3d67,0xbd353d35,0xbcacbd71,0x3d7f3bc9,0xbd043d5c,0xbd0ebd55,0x3d7dbc16,0xbc953d75,0xbd3ebd2c,
0xbd7b3c48,0x3cdbbd67,0x3cf13d62,0xbd7dbc16,0x3d6d3cc4,0xbd5c3d04,0x3bc9bd7f,0x3d3e3d2c,0xbd0ebd55,0x3d803b49,0xbd223d46,0xbc79bd78,0x3d80,0xbd4ebd18,0x3d75bc95,0xbcac3d71,
0x3d553d0e,0xbd713cac,0x3c95bd75,0x3d183d4e,0xbcc4bd6d,0x3d783c79,0xbd463d22,0xbb49bd80,0xbc483d7b,0xbd2cbd3e,0x3d7fbbc9,0xbd043d5c,0x3d35bd35,0x3c163d7d,0xbd62bcf1,0x3d67bcdb,
0xbd353d35,0x3b49bd80,0x3d223d46,0xbd7dbc16,0x3d55bd0e,0xbc793d78,0xbcf1bd62,0x3d713cac,0xbd6d3cc4,0x3cdbbd67,0x3c953d75,0xbd5cbd04,0x3d7bbc48,0xbd183d4e,0xbbc9bd7f,0x3d3e3d2c,
0x3d80,0xbd2cbd3e,0x3d7f3bc9,0xbd4e3d18,0x3c48bd7b,0x3d043d5c,0xbd75bc95,0x3d67bcdb,0xbcc43d6d,0xbcacbd71,0x3d623cf1,0xbd783c79,0x3d0ebd55,0x3c163d7d,0xbd46bd22,0x3d80bb49,
0xbd7bbc48,0x3d71bcac,0xbd223d46,0x3c16bd7d,0x3d35bd35,0xbc793d78,0xbc95bd75,0x3d3e3d2c,0x3d0ebd55,0xbb493d80,0xbcf1bd62,0x3d5c3d04,0x3cc43d6d,0xbd4ebd18,0x3d7f3bc9,0xbd673cdb,
0x3d55bd0e,0xbcdb3d67,0xbbc9bd7f,0x3d183d4e,0x3d80,0xbd04bd5c,0x3d623cf1,0xbd803b49,0x3c483d7b,0xbd2cbd3e,0x3d753c95,0xbd783c79,0xbd6dbcc4,0x3d7dbc16,0xbd463d22,0x3cacbd71,
0x3d6dbcc4,0xbd3e3d2c,0x3cf1bd62,0xbc163d7d,0xbc48bd7b,0x3d043d5c,0xbd46bd22,0x3d713cac,0xbd353d35,0x3cdbbd67,0xbbc93d7f,0xbc79bd78,0x3d0e3d55,0xbd4ebd18,0x3d753c95,0xbd803b49,
0x3cc4bd6d,0xbb493d80,0xbc95bd75,0x3d183d4e,0xbd55bd0e,0x3d783c79,0xbd7f3bc9,0x3d67bcdb,0x3d80,0xbcacbd71,0x3d223d46,0xbd5cbd04,0x3d7b3c48,0xbd7d3c16,0x3d62bcf1,0xbd2c3d3e,
0xbd55bd0e,0x3d673cdb,0xbd75bc95,0x3d7d3c16,0xbcc4bd6d,0x3d043d5c,0xbd22bd46,0x3d3e3d2c,0x3c48bd7b,0xbb493d80,0xbbc9bd7f,0x3c793d78,0x3d35bd35,0xbd183d4e,0x3cf1bd62,0xbcac3d71,
0x3d7bbc48,0xbd713cac,0x3d62bcf1,0xbd4e3d18,0x3d6d3cc4,0xbd78bc79,0x3d7f3bc9,0xbd803b49,0x3d0e3d55,0xbd2cbd3e,0x3d463d22,0xbd5cbd04,0x3d80,0xbc16bd7d,0x3c953d75,0xbcdbbd67,
0xbd800000,0x3b49bd80,0x3d7f3bc9,0xbc163d7d,0xbd7bbc48,0x3c79bd78,0x3d753c95,0xbcac3d71,0xbd6dbcc4,0x3cdbbd67,0x3d623cf1,0xbd043d5c,0xbd55bd0e,0x3d18bd4e,0x3d463d22,0xbd2c3d3e,
0xbd35bd35,0x3d3ebd2c,0x3d223d46,0xbd4e3d18,0xbd0ebd55,0x3d5cbd04,0x3cf13d62,0xbd673cdb,0xbcc4bd6d,0x3d71bcac,0x3c953d75,0xbd783c79,0xbc48bd7b,0x3d7dbc16,0x3bc93d7f,0xbd803b49,
0xbd0ebd55,0x3d71bcac,0x3bc93d7f,0xbd7dbc16,0xbd800000,0x3c79bd78,0x3d623cf1,0xbd2c3d3e,0x3d7bbc48,0xbb493d80,0xbd75bc95,0x3d04bd5c,0x3cc4bd6d,0x3d4e3d18,0xbd463d22,0xbcdbbd67,
0xbc483d7b,0xbd67bcdb,0x3d22bd46,0x3d183d4e,0x3d353d35,0xbd5c3d04,0xbc95bd75,0x3d80bb49,0xbd55bd0e,0x3d3ebd2c,0x3cf13d62,0xbd783c79,0xbd6d3cc4,0xbc16bd7d,0x3d7f3bc9,0xbcac3d71,
0x3d6d3cc4,0xbd3e3d2c,0xbc95bd75,0x3d7d3c16,0xbd0e3d55,0xbd04bd5c,0x3d7fbbc9,0xbcac3d71,0xbd800000,0x3cdbbd67,0x3d223d46,0xbd783c79,0x3c48bd7b,0x3d4e3d18,0xbd623cf1,0xbb49bd80,
0x3cc43d6d,0xbd80bb49,0x3cf1bd62,0x3d183d4e,0xbd7b3c48,0x3c79bd78,0x3d463d22,0xbd673cdb,0xbd35bd35,0x3d71bcac,0xbbc93d7f,0xbd5cbd04,0x3d55bd0e,0x3c163d7d,0xbd75bc95,0x3d2cbd3e,
0xbc48bd7b,0x3d673cdb,0xbd623cf1,0x3c16bd7d,0xbcc43d6d,0xbd04bd5c,0x3d7f3bc9,0xbd2c3d3e,0x3d55bd0e,0xbb493d80,0xbd46bd22,0x3d78bc79,0xbd800000,0x3d18bd4e,0x3c953d75,0xbd71bcac,
0xbd0e3d55,0xbcacbd71,0x3d753c95,0xbd4e3d18,0x3d6dbcc4,0xbc793d78,0xbd22bd46,0x3d80bb49,0xbd7bbc48,0x3d3ebd2c,0x3bc93d7f,0xbd5cbd04,0x3d353d35,0xbd7d3c16,0x3cf1bd62,0x3cdb3d67,
0xbd35bd35,0x3d803b49,0xbd463d22,0x3c16bd7d,0x3d0e3d55,0xbd78bc79,0x3d62bcf1,0xbcac3d71,0xbcc4bd6d,0x3d673cdb,0xbd753c95,0x3d04bd5c,0x3c483d7b,0xbd4ebd18,0x3d7fbbc9,0xbd2c3d3e,
0xbd800000,0x3d3ebd2c,0xbbc93d7f,0xbd18bd4e,0x3d7b3c48,0xbd5c3d04,0x3c95bd75,0x3cdb3d67,0xbd6dbcc4,0x3d71bcac,0xbcf13d62,0xbc79bd78,0x3d553d0e,0xbd7d3c16,0x3d22bd46,0x3b493d80,
0x3c48bd7b,0x3cac3d71,0xbd46bd22,0x3d7d3c16,0x3d353d35,0xbd78bc79,0x3d75bc95,0xbd2c3d3e,0x3d553d0e,0xbd80bb49,0x3d62bcf1,0xbd043d5c,0xbd6d3cc4,0x3d18bd4e,0xbbc93d7f,0xbcdbbd67,
0x3d0e3d55,0xbd67bcdb,0x3d7fbbc9,0xbd4e3d18,0xbd800000,0x3d5cbd04,0xbcf13d62,0xbb49bd80,0xbd7b3c48,0x3d3ebd2c,0xbc953d75,0xbc79bd78,0x3cc4bd6d,0x3c163d7d,0xbd22bd46,0x3d713cac,
0x3cc43d6d,0xbd2cbd3e,0x3d623cf1,0xbd7dbc16,0x3d7bbc48,0xbd5c3d04,0x3d22bd46,0xbcac3d71,0xbd35bd35,0x3d673cdb,0xbd7fbbc9,0x3d78bc79,0xbd553d0e,0x3d18bd4e,0xbc953d75,0xbb49bd80,
0x3d6d3cc4,0xbd80bb49,0x3d75bc95,0xbd4e3d18,0x3d0ebd55,0xbc793d78,0xbbc9bd7f,0x3cdb3d67,0xbd800000,0x3d71bcac,0xbd463d22,0x3d04bd5c,0xbc483d7b,0xbc16bd7d,0x3cf13d62,0xbd3ebd2c,
0x3d0ebd55,0xbcdb3d67,0x3c95bd75,0xbc163d7d,0x3d6dbcc4,0xbd5c3d04,0x3d46bd22,0xbd2c3d3e,0x3d7b3c48,0xbd80bb49,0x3d7fbbc9,0xbd783c79,0x3d353d35,0xbd4ebd18,0x3d623cf1,0xbd71bcac,
0x3c483d7b,0xbcacbd71,0x3cf13d62,0xbd18bd4e,0xbcc43d6d,0x3c79bd78,0xbbc93d7f,0xbb49bd80,0xbd553d0e,0x3d3ebd2c,0xbd223d46,0x3d04bd5c,0xbd800000,0x3d7dbc16,0xbd753c95,0x3d67bcdb,
0x3d80,0x3b49bd80,0xbbc93d7f,0x3c16bd7d,0xbc483d7b,0x3c79bd78,0xbc953d75,0x3cacbd71,0xbcc43d6d,0x3cdbbd67,0xbcf13d62,0x3d04bd5c,0xbd0e3d55,0x3d18bd4e,0xbd223d46,0x3d2cbd3e,
0xbd353d35,0x3d3ebd2c,0xbd463d22,0x3d4ebd18,0xbd553d0e,0x3d5cbd04,0xbd623cf1,0x3d67bcdb,0xbd6d3cc4,0x3d71bcac,0xbd753c95,0x3d78bc79,0xbd7b3c48,0x3d7dbc16,0xbd7f3bc9,0x3d80bb49,
0xbd553d0e,0x3d71bcac,0xbd7f3bc9,0x3d7d3c16,0x3d80,0x3c79bd78,0xbcf13d62,0x3d2cbd3e,0xbc48bd7b,0xbb493d80,0x3c95bd75,0xbd043d5c,0xbd6dbcc4,0x3d4e3d18,0xbd22bd46,0x3cdb3d67,
0x3d7b3c48,0xbd67bcdb,0x3d463d22,0xbd18bd4e,0x3d35bd35,0xbd5c3d04,0x3d75bc95,0xbd803b49,0xbd0e3d55,0x3d3ebd2c,0xbd623cf1,0x3d78bc79,0x3cc43d6d,0xbc16bd7d,0xbbc93d7f,0x3cacbd71,
0x3cc4bd6d,0xbd3e3d2c,0x3d75bc95,0xbd7dbc16,0x3d553d0e,0xbd04bd5c,0x3bc93d7f,0x3cacbd71,0x3d80,0x3cdbbd67,0xbd463d22,0x3d78bc79,0xbd7bbc48,0x3d4e3d18,0xbcf1bd62,0x3b493d80,
0x3d6dbcc4,0xbd80bb49,0x3d623cf1,0xbd18bd4e,0x3c483d7b,0x3c79bd78,0xbd223d46,0x3d67bcdb,0xbd353d35,0x3d71bcac,0xbd7fbbc9,0x3d5c3d04,0xbd0ebd55,0x3c163d7d,0x3c95bd75,0xbd2c3d3e,
0xbd7b3c48,0x3d673cdb,0xbcf1bd62,0xbc163d7d,0x3d6d3cc4,0xbd04bd5c,0xbbc93d7f,0x3d2cbd3e,0xbd0ebd55,0xbb493d80,0x3d22bd46,0xbd783c79,0x3d80,0x3d18bd4e,0xbd753c95,0x3d713cac,
0x3d553d0e,0xbcacbd71,0xbc953d75,0x3d4ebd18,0xbcc4bd6d,0xbc793d78,0x3d46bd22,0xbd803b49,0xbc483d7b,0x3d3ebd2c,0xbd7f3bc9,0x3d5c3d04,0x3d35bd35,0xbd7d3c16,0x3d623cf1,0xbcdbbd67,
0xbd353d35,0x3d803b49,0xbd22bd46,0xbc163d7d,0x3d55bd0e,0xbd78bc79,0x3cf13d62,0x3cacbd71,0xbd6d3cc4,0x3d673cdb,0xbc95bd75,0xbd043d5c,0x3d7bbc48,0xbd4ebd18,0x3bc93d7f,0x3d2cbd3e,
0x3d80,0x3d3ebd2c,0xbd7fbbc9,0x3d183d4e,0x3c48bd7b,0xbd5c3d04,0x3d753c95,0xbcdbbd67,0xbcc43d6d,0x3d71bcac,0xbd62bcf1,0x3c793d78,0x3d0ebd55,0xbd7d3c16,0x3d463d22,0xbb49bd80,
0xbd7bbc48,0x3cac3d71,0x3d22bd46,0xbd7dbc16,0x3d35bd35,0xbd78bc79,0x3c953d75,0x3d2cbd3e,0x3d0ebd55,0xbd80bb49,0x3cf13d62,0x3d04bd5c,0x3cc43d6d,0x3d18bd4e,0xbd7fbbc9,0x3cdb3d67,
0x3d55bd0e,0xbd67bcdb,0x3bc93d7f,0x3d4ebd18,0x3d80,0x3d5cbd04,0xbd62bcf1,0x3b493d80,0x3c483d7b,0x3d3ebd2c,0xbd75bc95,0x3c793d78,0xbd6dbcc4,0x3c163d7d,0x3d46bd22,0xbd71bcac,
0x3d6dbcc4,0xbd2cbd3e,0xbcf13d62,0x3d7d3c16,0xbc48bd7b,0xbd5c3d04,0x3d463d22,0x3cacbd71,0xbd353d35,0x3d673cdb,0x3bc9bd7f,0xbd783c79,0x3d0e3d55,0x3d18bd4e,0xbd75bc95,0x3b493d80,
0x3cc4bd6d,0xbd80bb49,0x3c953d75,0x3d4ebd18,0xbd55bd0e,0xbc793d78,0x3d7fbbc9,0xbcdbbd67,0x3d80,0x3d71bcac,0xbd22bd46,0xbd043d5c,0x3d7b3c48,0xbc16bd7d,0xbd623cf1,0x3d3e3d2c,
0xbd55bd0e,0xbcdb3d67,0x3d753c95,0x3c16bd7d,0xbcc4bd6d,0xbd5c3d04,0x3d223d46,0x3d2cbd3e,0x3c48bd7b,0xbd80bb49,0x3bc93d7f,0x3d78bc79,0x3d35bd35,0xbd4ebd18,0xbcf13d62,0x3d713cac,
0x3d7bbc48,0xbcacbd71,0xbd623cf1,0x3d183d4e,0x3d6d3cc4,0x3c79bd78,0xbd7fbbc9,0x3b493d80,0x3d0e3d55,0x3d3ebd2c,0xbd46bd22,0xbd043d5c,0x3d80,0x3d7dbc16,0xbc95bd75,0xbd673cdb,
0xbd800000,0x3d803b49,0xbd7fbbc9,0x3d7d3c16,0xbd7bbc48,0x3d783c79,0xbd75bc95,0x3d713cac,0xbd6dbcc4,0x3d673cdb,0xbd62bcf1,0x3d5c3d04,0xbd55bd0e,0x3d4e3d18,0xbd46bd22,0x3d3e3d2c,
0xbd35bd35,0x3d2c3d3e,0xbd22bd46,0x3d183d4e,0xbd0ebd55,0x3d043d5c,0xbcf1bd62,0x3cdb3d67,0xbcc4bd6d,0x3cac3d71,0xbc95bd75,0x3c793d78,0xbc48bd7b,0x3c163d7d,0xbbc9bd7f,0x3b493d80,
0xbd0ebd55,0x3cac3d71,0xbbc9bd7f,0xbc163d7d,0xbd800000,0x3d783c79,0xbd62bcf1,0x3d3e3d2c,0x3d7bbc48,0xbd80bb49,0x3d753c95,0xbd5cbd04,0x3cc4bd6d,0xbd183d4e,0x3d46bd22,0xbd673cdb,
0xbc483d7b,0x3cdbbd67,0xbd223d46,0x3d4ebd18,0x3d353d35,0xbd04bd5c,0x3c953d75,0xbb49bd80,0xbd55bd0e,0x3d2c3d3e,0xbcf1bd62,0x3c793d78,0xbd6d3cc4,0x3d7dbc16,0xbd7fbbc9,0x3d713cac,
0x3d6d3cc4,0xbd2cbd3e,0x3c953d75,0x3c16bd7d,0xbd0e3d55,0x3d5cbd04,0xbd7f3bc9,0x3d713cac,0xbd800000,0x3d673cdb,0xbd22bd46,0x3c793d78,0x3c48bd7b,0xbd183d4e,0x3d62bcf1,0xbd803b49,
0x3cc43d6d,0x3b49bd80,0xbcf13d62,0x3d4ebd18,0xbd7b3c48,0x3d783c79,0xbd46bd22,0x3cdb3d67,0xbd35bd35,0x3cac3d71,0x3bc9bd7f,0xbd043d5c,0x3d55bd0e,0xbd7d3c16,0x3d753c95,0xbd3ebd2c,
0xbc48bd7b,0xbcdb3d67,0x3d62bcf1,0xbd7dbc16,0xbcc43d6d,0x3d5cbd04,0xbd7fbbc9,0x3d3e3d2c,0x3d55bd0e,0xbd80bb49,0x3d463d22,0xbc79bd78,0xbd800000,0x3d4e3d18,0xbc95bd75,0xbcac3d71,
0xbd0e3d55,0x3d71bcac,0xbd75bc95,0x3d183d4e,0x3d6dbcc4,0xbd78bc79,0x3d223d46,0xbb49bd80,0xbd7bbc48,0x3d2c3d3e,0xbbc9bd7f,0xbd043d5c,0x3d353d35,0xbc16bd7d,0xbcf13d62,0x3d67bcdb,
0xbd35bd35,0xbb493d80,0x3d46bd22,0xbd7dbc16,0x3d0e3d55,0x3c79bd78,0xbd623cf1,0x3d713cac,0xbcc4bd6d,0xbcdb3d67,0x3d75bc95,0xbd5cbd04,0x3c483d7b,0x3d18bd4e,0xbd7f3bc9,0x3d3e3d2c,
0xbd800000,0x3d2c3d3e,0x3bc9bd7f,0xbd4e3d18,0x3d7b3c48,0xbd04bd5c,0xbc953d75,0x3d67bcdb,0xbd6dbcc4,0x3cac3d71,0x3cf1bd62,0xbd783c79,0x3d553d0e,0xbc16bd7d,0xbd223d46,0x3d80bb49,
0x3c48bd7b,0xbd713cac,0x3d463d22,0x3c16bd7d,0x3d353d35,0x3c79bd78,0xbd753c95,0x3d3e3d2c,0x3d553d0e,0x3b49bd80,0xbd623cf1,0x3d5c3d04,0xbd6d3cc4,0x3d4e3d18,0x3bc9bd7f,0xbd673cdb,
0x3d0e3d55,0x3cdbbd67,0xbd7f3bc9,0x3d183d4e,0xbd800000,0x3d043d5c,0x3cf1bd62,0xbd803b49,0xbd7b3c48,0x3d2c3d3e,0x3c95bd75,0xbd783c79,0x3cc4bd6d,0xbd7d3c16,0x3d223d46,0x3cacbd71,
0x3cc43d6d,0x3d3ebd2c,0xbd62bcf1,0xbc163d7d,0x3d7bbc48,0xbd04bd5c,0xbd223d46,0x3d713cac,0xbd35bd35,0xbcdb3d67,0x3d7f3bc9,0xbc79bd78,0xbd553d0e,0x3d4e3d18,0x3c95bd75,0xbd803b49,
0x3d6d3cc4,0x3b49bd80,0xbd753c95,0x3d183d4e,0x3d0ebd55,0xbd78bc79,0x3bc93d7f,0x3d67bcdb,0xbd800000,0x3cac3d71,0x3d46bd22,0xbd5cbd04,0xbc483d7b,0x3d7dbc16,0xbcf1bd62,0xbd2c3d3e,
0x3d0ebd55,0xbd67bcdb,0xbc953d75,0x3d7d3c16,0x3d6dbcc4,0xbd04bd5c,0xbd463d22,0x3d3e3d2c,0x3d7b3c48,0x3b49bd80,0xbd7f3bc9,0x3c793d78,0x3d353d35,0x3d18bd4e,0xbd62bcf1,0xbcac3d71,
0x3c483d7b,0x3d71bcac,0xbcf1bd62,0xbd4e3d18,0xbcc43d6d,0x3d783c79,0x3bc9bd7f,0xbd803b49,0xbd553d0e,0x3d2c3d3e,0x3d22bd46,0xbd5cbd04,0xbd800000,0x3c163d7d,0x3d75bc95,0xbcdbbd67,
0x3d80,0x3d803b49,0x3bc9bd7f,0xbd7dbc16,0xbc483d7b,0x3d783c79,0x3c95bd75,0xbd71bcac,0xbcc43d6d,0x3d673cdb,0x3cf1bd62,0xbd5cbd04,0xbd0e3d55,0x3d4e3d18,0x3d22bd46,0xbd3ebd2c,
0xbd353d35,0x3d2c3d3e,0x3d46bd22,0xbd18bd4e,0xbd553d0e,0x3d043d5c,0x3d62bcf1,0xbcdbbd67,0xbd6d3cc4,0x3cac3d71,0x3d75bc95,0xbc79bd78,0xbd7b3c48,0x3c163d7d,0x3d7fbbc9,0xbb49bd80,
0xbd553d0e,0x3cac3d71,0x3d7fbbc9,0x3c16bd7d,0x3d80,0x3d783c79,0x3cf1bd62,0xbd3ebd2c,0xbc48bd7b,0xbd80bb49,0xbc953d75,0x3d5c3d04,0xbd6dbcc4,0xbd183d4e,0x3d223d46,0x3d67bcdb,
0x3d7b3c48,0x3cdbbd67,0xbd46bd22,0xbd4e3d18,0x3d35bd35,0xbd04bd5c,0xbd753c95,0x3b493d80,0xbd0e3d55,0x3d2c3d3e,0x3d62bcf1,0xbc79bd78,0x3cc43d6d,0x3d7dbc16,0x3bc9bd7f,0xbd71bcac,
0x3cc4bd6d,0xbd2cbd3e,0xbd753c95,0xbc163d7d,0x3d553d0e,0x3d5cbd04,0xbbc9bd7f,0xbd71bcac,0x3d80,0x3d673cdb,0x3d46bd22,0xbc79bd78,0xbd7bbc48,0xbd183d4e,0x3cf13d62,0x3d80bb49,
0x3d6dbcc4,0x3b49bd80,0xbd62bcf1,0xbd4e3d18,0x3c483d7b,0x3d783c79,0x3d22bd46,0xbcdbbd67,0xbd353d35,0x3cac3d71,0x3d7f3bc9,0x3d04bd5c,0xbd0ebd55,0xbd7d3c16,0xbc953d75,0x3d3e3d2c,
0xbd7b3c48,0xbcdb3d67,0x3cf13d62,0x3d7d3c16,0x3d6d3cc4,0x3d5cbd04,0x3bc9bd7f,0xbd3ebd2c,0xbd0ebd55,0xbd80bb49,0xbd223d46,0x3c793d78,0x3d80,0x3d4e3d18,0x3d75bc95,0x3cacbd71,
0x3d553d0e,0x3d71bcac,0x3c95bd75,0xbd18bd4e,0xbcc4bd6d,0xbd78bc79,0xbd463d22,0x3b493d80,0xbc483d7b,0x3d2c3d3e,0x3d7fbbc9,0x3d04bd5c,0x3d35bd35,0xbc16bd7d,0xbd62bcf1,0xbd673cdb,
0xbd353d35,0xbb493d80,0x3d223d46,0x3d7d3c16,0x3d55bd0e,0x3c79bd78,0xbcf1bd62,0xbd71bcac,0xbd6d3cc4,0xbcdb3d67,0x3c953d75,0x3d5c3d04,0x3d7bbc48,0x3d18bd4e,0xbbc9bd7f,0xbd3ebd2c,
0x3d80,0x3d2c3d3e,0x3d7f3bc9,0x3d4ebd18,0x3c48bd7b,0xbd04bd5c,0xbd75bc95,0xbd673cdb,0xbcc43d6d,0x3cac3d71,0x3d623cf1,0x3d78bc79,0x3d0ebd55,0xbc16bd7d,0xbd46bd22,0xbd803b49,
0xbd7bbc48,0xbd713cac,0xbd223d46,0xbc163d7d,0x3d35bd35,0x3c79bd78,0xbc95bd75,0xbd3ebd2c,0x3d0ebd55,0x3b49bd80,0xbcf1bd62,0xbd5cbd04,0x3cc43d6d,0x3d4e3d18,0x3d7f3bc9,0x3d67bcdb,
0x3d55bd0e,0x3cdbbd67,0xbbc9bd7f,0xbd18bd4e,0x3d80,0x3d043d5c,0x3d623cf1,0x3d80bb49,0x3c483d7b,0x3d2c3d3e,0x3d753c95,0x3d78bc79,0xbd6dbcc4,0xbd7d3c16,0xbd463d22,0xbcac3d71,
0x3d6dbcc4,0x3d3ebd2c,0x3cf1bd62,0x3c16bd7d,0xbc48bd7b,0xbd04bd5c,0xbd46bd22,0xbd71bcac,0xbd353d35,0xbcdb3d67,0xbbc93d7f,0x3c793d78,0x3d0e3d55,0x3d4e3d18,0x3d753c95,0x3d80bb49,
0x3cc4bd6d,0x3b49bd80,0xbc95bd75,0xbd18bd4e,0xbd55bd0e,0xbd78bc79,0xbd7f3bc9,0xbd673cdb,0x3d80,0x3cac3d71,0x3d223d46,0x3d5c3d04,0x3d7b3c48,0x3d7dbc16,0x3d62bcf1,0x3d2cbd3e,
0xbd55bd0e,0xbd67bcdb,0xbd75bc95,0xbd7dbc16,0xbcc4bd6d,0xbd04bd5c,0xbd22bd46,0xbd3ebd2c,0x3c48bd7b,0x3b49bd80,0xbbc9bd7f,0xbc79bd78,0x3d35bd35,0x3d18bd4e,0x3cf1bd62,0x3cacbd71,
0x3d7bbc48,0x3d71bcac,0x3d62bcf1,0x3d4ebd18,0x3d6d3cc4,0x3d783c79,0x3d7f3bc9,0x3d80bb49,0x3d0e3d55,0x3d2c3d3e,0x3d463d22,0x3d5c3d04,0x3d80,0x3c163d7d,0x3c953d75,0x3cdb3d67,
0xbd800000,0xbb493d80,0x3d7f3bc9,0x3c16bd7d,0xbd7bbc48,0xbc793d78,0x3d753c95,0x3cacbd71,0xbd6dbcc4,0xbcdb3d67,0x3d623cf1,0x3d04bd5c,0xbd55bd0e,0xbd183d4e,0x3d463d22,0x3d2cbd3e,
0xbd35bd35,0xbd3e3d2c,0x3d223d46,0x3d4ebd18,0xbd0ebd55,0xbd5c3d04,0x3cf13d62,0x3d67bcdb,0xbcc4bd6d,0xbd713cac,0x3c953d75,0x3d78bc79,0xbc48bd7b,0xbd7d3c16,0x3bc93d7f,0x3d80bb49,
0xbd0ebd55,0xbd713cac,0x3bc93d7f,0x3d7d3c16,0xbd800000,0xbc793d78,0x3d623cf1,0x3d2cbd3e,0x3d7bbc48,0x3b49bd80,0xbd75bc95,0xbd043d5c,0x3cc4bd6d,0xbd4ebd18,0xbd463d22,0x3cdb3d67,
0xbc483d7b,0x3d673cdb,0x3d22bd46,0xbd18bd4e,0x3d353d35,0x3d5cbd04,0xbc95bd75,0xbd803b49,0xbd55bd0e,0xbd3e3d2c,0x3cf13d62,0x3d78bc79,0xbd6d3cc4,0x3c163d7d,0x3d7f3bc9,0x3cacbd71,
0x3d6d3cc4,0x3d3ebd2c,0xbc95bd75,0xbd7dbc16,0xbd0e3d55,0x3d043d5c,0x3d7fbbc9,0x3cacbd71,0xbd800000,0xbcdb3d67,0x3d223d46,0x3d78bc79,0x3c48bd7b,0xbd4ebd18,0xbd623cf1,0x3b493d80,
0x3cc43d6d,0x3d803b49,0x3cf1bd62,0xbd18bd4e,0xbd7b3c48,0xbc793d78,0x3d463d22,0x3d67bcdb,0xbd35bd35,0xbd713cac,0xbbc93d7f,0x3d5c3d04,0x3d55bd0e,0xbc16bd7d,0xbd75bc95,0xbd2c3d3e,
0xbc48bd7b,0xbd67bcdb,0xbd623cf1,0xbc163d7d,0xbcc43d6d,0x3d043d5c,0x3d7f3bc9,0x3d2cbd3e,0x3d55bd0e,0x3b49bd80,0xbd46bd22,0xbd783c79,0xbd800000,0xbd183d4e,0x3c953d75,0x3d713cac,
0xbd0e3d55,0x3cac3d71,0x3d753c95,0x3d4ebd18,0x3d6dbcc4,0x3c79bd78,0xbd22bd46,0xbd803b49,0xbd7bbc48,0xbd3e3d2c,0x3bc93d7f,0x3d5c3d04,0x3d353d35,0x3d7dbc16,0x3cf1bd62,0xbcdbbd67,
0xbd35bd35,0xbd80bb49,0xbd463d22,0xbc163d7d,0x3d0e3d55,0x3d783c79,0x3d62bcf1,0x3cacbd71,0xbcc4bd6d,0xbd67bcdb,0xbd753c95,0xbd043d5c,0x3c483d7b,0x3d4e3d18,0x3d7fbbc9,0x3d2cbd3e,
0xbd800000,0xbd3e3d2c,0xbbc93d7f,0x3d183d4e,0x3d7b3c48,0x3d5cbd04,0x3c95bd75,0xbcdbbd67,0xbd6dbcc4,0xbd713cac,0xbcf13d62,0x3c793d78,0x3d553d0e,0x3d7dbc16,0x3d22bd46,0xbb49bd80,
0x3c48bd7b,0xbcacbd71,0xbd46bd22,0xbd7dbc16,0x3d353d35,0x3d783c79,0x3d75bc95,0x3d2cbd3e,0x3d553d0e,0x3d803b49,0x3d62bcf1,0x3d04bd5c,0xbd6d3cc4,0xbd183d4e,0xbbc93d7f,0x3cdb3d67,
0x3d0e3d55,0x3d673cdb,0x3d7fbbc9,0x3d4ebd18,0xbd800000,0xbd5c3d04,0xbcf13d62,0x3b493d80,0xbd7b3c48,0xbd3e3d2c,0xbc953d75,0x3c793d78,0x3cc4bd6d,0xbc16bd7d,0xbd22bd46,0xbd71bcac,
0x3cc43d6d,0x3d2c3d3e,0x3d623cf1,0x3d7d3c16,0x3d7bbc48,0x3d5cbd04,0x3d22bd46,0x3cacbd71,0xbd35bd35,0xbd67bcdb,0xbd7fbbc9,0xbd783c79,0xbd553d0e,0xbd183d4e,0xbc953d75,0x3b493d80,
0x3d6d3cc4,0x3d803b49,0x3d75bc95,0x3d4ebd18,0x3d0ebd55,0x3c79bd78,0xbbc9bd7f,0xbcdbbd67,0xbd800000,0xbd713cac,0xbd463d22,0xbd043d5c,0xbc483d7b,0x3c163d7d,0x3cf13d62,0x3d3e3d2c,
0x3d0ebd55,0x3cdbbd67,0x3c95bd75,0x3c16bd7d,0x3d6dbcc4,0x3d5cbd04,0x3d46bd22,0x3d2cbd3e,0x3d7b3c48,0x3d803b49,0x3d7fbbc9,0x3d78bc79,0x3d353d35,0x3d4e3d18,0x3d623cf1,0x3d713cac,
0x3c483d7b,0x3cac3d71,0x3cf13d62,0x3d183d4e,0xbcc43d6d,0xbc793d78,0xbbc93d7f,0x3b493d80,0xbd553d0e,0xbd3e3d2c,0xbd223d46,0xbd043d5c,0xbd800000,0xbd7d3c16,0xbd753c95,0xbd673cdb,
0x3d80,0xbbc93d7f,0xbc483d7b,0xbc953d75,0xbcc43d6d,0xbcf13d62,0xbd0e3d55,0xbd223d46,0xbd353d35,0xbd463d22,0xbd553d0e,0xbd623cf1,0xbd6d3cc4,0xbd753c95,0xbd7b3c48,0xbd7f3bc9,
0xbd800000,0xbd7fbbc9,0xbd7bbc48,0xbd75bc95,0xbd6dbcc4,0xbd62bcf1,0xbd55bd0e,0xbd46bd22,0xbd35bd35,0xbd22bd46,0xbd0ebd55,0xbcf1bd62,0xbcc4bd6d,0xbc95bd75,0xbc48bd7b,0xbbc9bd7f,
0xbd6d3cc4,0xbd7f3bc9,0xbd7bbc48,0xbd62bcf1,0x3d80,0xbc953d75,0xbd0e3d55,0xbd463d22,0x3cc4bd6d,0x3d22bd46,0x3d55bd0e,0x3d75bc95,0xbd35bd35,0xbcf1bd62,0xbc48bd7b,0x3bc9bd7f,
0x3cc43d6d,0x3bc93d7f,0xbc483d7b,0xbcf13d62,0x3d800000,0x3d753c95,0x3d553d0e,0x3d223d46,0xbd6dbcc4,0xbd46bd22,0xbd0ebd55,0xbc95bd75,0xbd353d35,0xbd623cf1,0xbd7b3c48,0xbd7fbbc9,
0x3d35bd35,0x3d75bc95,0x3d7b3c48,0x3d463d22,0x3cc43d6d,0xbbc93d7f,0xbd0e3d55,0xbd623cf1,0x3d80,0xbcf13d62,0xbd553d0e,0xbd7f3bc9,0xbd6dbcc4,0xbd22bd46,0xbc48bd7b,0x3c95bd75,
0x3d353d35,0x3c953d75,0xbc483d7b,0xbd223d46,0xbd6d3cc4,0xbd7fbbc9,0xbd55bd0e,0xbcf1bd62,0xbd800000,0xbd62bcf1,0xbd0ebd55,0xbbc9bd7f,0x3cc4bd6d,0x3d46bd22,0x3d7bbc48,0x3d753c95,
0xbd6dbcc4,0xbcf1bd62,0x3c48bd7b,0x3d46bd22,0x3d353d35,0x3bc93d7f,0xbd0e3d55,0xbd753c95,0xbcc4bd6d,0x3c95bd75,0x3d55bd0e,0x3d7f3bc9,0x3d80,0xbd223d46,0xbd7b3c48,0xbd62bcf1,
0xbcc43d6d,0xbd623cf1,0xbd7bbc48,0xbd22bd46,0x3d35bd35,0x3d7fbbc9,0x3d553d0e,0x3c953d75,0xbd6d3cc4,0xbd75bc95,0xbd0ebd55,0x3bc9bd7f,0x3d800000,0x3d463d22,0x3c483d7b,0xbcf13d62,
0xbd800000,0xbd22bd46,0x3c48bd7b,0x3d62bcf1,0x3d6d3cc4,0x3c953d75,0xbd0e3d55,0xbd7f3bc9,0xbd35bd35,0x3bc9bd7f,0x3d55bd0e,0x3d753c95,0x3cc43d6d,0xbcf13d62,0xbd7b3c48,0xbd46bd22,
0x3d80,0xbd463d22,0xbd7bbc48,0xbcf1bd62,0x3cc4bd6d,0x3d75bc95,0x3d553d0e,0x3bc93d7f,0xbd353d35,0xbd7fbbc9,0xbd0ebd55,0x3c95bd75,0x3d6dbcc4,0x3d623cf1,0x3c483d7b,0xbd223d46,
0xbcc4bd6d,0x3d22bd46,0x3d7b3c48,0x3c953d75,0x3d800000,0x3cf13d62,0xbd0e3d55,0xbd7fbbc9,0x3d6d3cc4,0x3bc93d7f,0xbd553d0e,0xbd62bcf1,0xbd353d35,0xbd75bc95,0xbc48bd7b,0x3d46bd22,
0x3d6dbcc4,0x3d463d22,0xbc483d7b,0xbd753c95,0x3d80,0xbd623cf1,0xbd55bd0e,0x3bc9bd7f,0xbcc43d6d,0xbd7f3bc9,0xbd0ebd55,0x3cf1bd62,0xbd35bd35,0x3c95bd75,0x3d7bbc48,0x3d223d46,
0x3d353d35,0xbcf13d62,0xbd7bbc48,0xbbc9bd7f,0x3d6dbcc4,0x3d223d46,0xbd0e3d55,0xbd75bc95,0xbd800000,0xbc95bd75,0x3d55bd0e,0x3d463d22,0xbcc43d6d,0xbd7fbbc9,0xbc48bd7b,0x3d62bcf1,
0x3d35bd35,0x3d623cf1,0xbc483d7b,0xbd7f3bc9,0xbcc4bd6d,0x3d46bd22,0x3d553d0e,0xbc953d75,0x3d80,0xbd753c95,0xbd0ebd55,0x3d22bd46,0x3d6d3cc4,0xbbc93d7f,0xbd7b3c48,0xbcf1bd62,
0x3cc4bd6d,0x3d753c95,0xbc483d7b,0xbd7fbbc9,0x3d35bd35,0x3d463d22,0xbd0e3d55,0xbd62bcf1,0x3d6dbcc4,0x3cf13d62,0xbd553d0e,0xbd22bd46,0x3d800000,0x3bc93d7f,0xbd7b3c48,0xbc95bd75,
0x3d6d3cc4,0xbc953d75,0xbd7bbc48,0x3bc9bd7f,0x3d353d35,0xbd223d46,0xbd55bd0e,0x3cf1bd62,0x3cc43d6d,0xbd623cf1,0xbd0ebd55,0x3d46bd22,0x3d80,0xbd7f3bc9,0xbc48bd7b,0x3d75bc95,
0xbd800000,0xbd7fbbc9,0xbd7bbc48,0xbd75bc95,0xbd6dbcc4,0xbd62bcf1,0xbd55bd0e,0xbd46bd22,0xbd35bd35,0xbd22bd46,0xbd0ebd55,0xbcf1bd62,0xbcc4bd6d,0xbc95bd75,0xbc48bd7b,0xbbc9bd7f,
0x8000bd80,0x3bc9bd7f,0x3c48bd7b,0x3c95bd75,0x3cc4bd6d,0x3cf1bd62,0x3d0ebd55,0x3d22bd46,0x3d35bd35,0x3d46bd22,0x3d55bd0e,0x3d62bcf1,0x3d6dbcc4,0x3d75bc95,0x3d7bbc48,0x3d7fbbc9,
0xbcc4bd6d,0xbbc9bd7f,0x3c48bd7b,0x3cf1bd62,0xbd800000,0xbd75bc95,0xbd55bd0e,0xbd22bd46,0x3d6d3cc4,0x3d463d22,0x3d0e3d55,0x3c953d75,0x3d35bd35,0x3d62bcf1,0x3d7bbc48,0x3d7f3bc9,
0xbd6d3cc4,0xbd7f3bc9,0xbd7bbc48,0xbd62bcf1,0x80003d80,0xbc953d75,0xbd0e3d55,0xbd463d22,0x3cc4bd6d,0x3d22bd46,0x3d55bd0e,0x3d75bc95,0xbd35bd35,0xbcf1bd62,0xbc48bd7b,0x3bc9bd7f,
0x3d353d35,0x3c953d75,0xbc483d7b,0xbd223d46,0xbd6d3cc4,0xbd7fbbc9,0xbd55bd0e,0xbcf1bd62,0xbd800000,0xbd62bcf1,0xbd0ebd55,0xbbc9bd7f,0x3cc4bd6d,0x3d46bd22,0x3d7bbc48,0x3d753c95,
0xbd353d35,0xbd753c95,0xbd7bbc48,0xbd46bd22,0xbcc4bd6d,0x3bc9bd7f,0x3d0ebd55,0x3d62bcf1,0x8000bd80,0x3cf1bd62,0x3d55bd0e,0x3d7fbbc9,0x3d6d3cc4,0x3d223d46,0x3c483d7b,0xbc953d75,
0x3cc4bd6d,0x3d62bcf1,0x3d7b3c48,0x3d223d46,0xbd353d35,0xbd7f3bc9,0xbd55bd0e,0xbc95bd75,0x3d6dbcc4,0x3d753c95,0x3d0e3d55,0xbbc93d7f,0xbd800000,0xbd46bd22,0xbc48bd7b,0x3cf1bd62,
0xbd6dbcc4,0xbcf1bd62,0x3c48bd7b,0x3d46bd22,0x3d353d35,0x3bc93d7f,0xbd0e3d55,0xbd753c95,0xbcc4bd6d,0x3c95bd75,0x3d55bd0e,0x3d7f3bc9,0x80003d80,0xbd223d46,0xbd7b3c48,0xbd62bcf1,
0x8000bd80,0x3d46bd22,0x3d7b3c48,0x3cf13d62,0xbcc43d6d,0xbd753c95,0xbd55bd0e,0xbbc9bd7f,0x3d35bd35,0x3d7f3bc9,0x3d0e3d55,0xbc953d75,0xbd6d3cc4,0xbd62bcf1,0xbc48bd7b,0x3d22bd46,
0xbd800000,0xbd22bd46,0x3c48bd7b,0x3d62bcf1,0x3d6d3cc4,0x3c953d75,0xbd0e3d55,0xbd7f3bc9,0xbd35bd35,0x3bc9bd7f,0x3d55bd0e,0x3d753c95,0x3cc43d6d,0xbcf13d62,0xbd7b3c48,0xbd46bd22,
0x3d6dbcc4,0x3d463d22,0xbc483d7b,0xbd753c95,0x80003d80,0xbd623cf1,0xbd55bd0e,0x3bc9bd7f,0xbcc43d6d,0xbd7f3bc9,0xbd0ebd55,0x3cf1bd62,0xbd35bd35,0x3c95bd75,0x3d7bbc48,0x3d223d46,
0x3cc43d6d,0xbd223d46,0xbd7bbc48,0xbc95bd75,0xbd800000,0xbcf1bd62,0x3d0ebd55,0x3d7f3bc9,0xbd6dbcc4,0xbbc9bd7f,0x3d55bd0e,0x3d623cf1,0x3d35bd35,0x3d753c95,0x3c483d7b,0xbd463d22,
0xbd353d35,0xbd62bcf1,0x3c48bd7b,0x3d7fbbc9,0x3cc43d6d,0xbd463d22,0xbd55bd0e,0x3c95bd75,0x8000bd80,0x3d75bc95,0x3d0e3d55,0xbd223d46,0xbd6dbcc4,0x3bc9bd7f,0x3d7bbc48,0x3cf13d62,
0x3d353d35,0xbcf13d62,0xbd7bbc48,0xbbc9bd7f,0x3d6dbcc4,0x3d223d46,0xbd0e3d55,0xbd75bc95,0xbd800000,0xbc95bd75,0x3d55bd0e,0x3d463d22,0xbcc43d6d,0xbd7fbbc9,0xbc48bd7b,0x3d62bcf1,
0x3d6d3cc4,0xbc953d75,0xbd7bbc48,0x3bc9bd7f,0x3d353d35,0xbd223d46,0xbd55bd0e,0x3cf1bd62,0x3cc43d6d,0xbd623cf1,0xbd0ebd55,0x3d46bd22,0x80003d80,0xbd7f3bc9,0xbc48bd7b,0x3d75bc95,
0xbcc43d6d,0xbd75bc95,0x3c48bd7b,0x3d7f3bc9,0xbd353d35,0xbd46bd22,0x3d0ebd55,0x3d623cf1,0xbd6d3cc4,0xbcf1bd62,0x3d55bd0e,0x3d223d46,0xbd800000,0xbbc9bd7f,0x3d7bbc48,0x3c953d75,
0x3d80,0xbd7fbbc9,0x3c48bd7b,0x3d753c95,0xbcc43d6d,0xbd62bcf1,0x3d0ebd55,0x3d463d22,0xbd353d35,0xbd22bd46,0x3d55bd0e,0x3cf13d62,0xbd6d3cc4,0xbc95bd75,0x3d7bbc48,0x3bc93d7f,
0xbd800000,0x3bc9bd7f,0x3d7b3c48,0xbc953d75,0xbd6dbcc4,0x3cf1bd62,0x3d553d0e,0xbd223d46,0xbd35bd35,0x3d46bd22,0x3d0e3d55,0xbd623cf1,0xbcc4bd6d,0x3d75bc95,0x3c483d7b,0xbd7f3bc9,
0xbd6d3cc4,0xbbc9bd7f,0x3d7b3c48,0xbcf13d62,0x3d80,0xbd75bc95,0x3d0ebd55,0x3d223d46,0x3cc4bd6d,0x3d463d22,0xbd553d0e,0xbc95bd75,0xbd35bd35,0x3d62bcf1,0x3c483d7b,0xbd7fbbc9,
0x3cc43d6d,0xbd7f3bc9,0x3c48bd7b,0x3d623cf1,0x3d800000,0xbc953d75,0xbd55bd0e,0x3d46bd22,0xbd6dbcc4,0x3d22bd46,0x3d0e3d55,0xbd753c95,0xbd353d35,0xbcf1bd62,0x3d7bbc48,0xbbc93d7f,
0x3d35bd35,0x3c953d75,0xbd7bbc48,0x3d22bd46,0x3cc43d6d,0xbd7fbbc9,0x3d0ebd55,0x3cf13d62,0x3d80,0xbd62bcf1,0x3d55bd0e,0x3bc93d7f,0xbd6dbcc4,0x3d46bd22,0x3c483d7b,0xbd75bc95,
0x3d353d35,0xbd753c95,0x3c48bd7b,0x3d463d22,0xbd6d3cc4,0x3bc9bd7f,0x3d553d0e,0xbd623cf1,0xbd800000,0x3cf1bd62,0x3d0e3d55,0xbd7f3bc9,0x3cc4bd6d,0x3d223d46,0xbd7b3c48,0x3c95bd75,
0xbd6dbcc4,0x3d62bcf1,0xbc483d7b,0xbd22bd46,0x3d353d35,0xbd7f3bc9,0x3d0ebd55,0x3c953d75,0xbcc4bd6d,0x3d753c95,0xbd553d0e,0x3bc9bd7f,0x3d80,0xbd46bd22,0x3d7bbc48,0xbcf13d62,
0xbcc43d6d,0xbcf1bd62,0x3d7b3c48,0xbd463d22,0x3d35bd35,0x3bc93d7f,0xbd55bd0e,0x3d75bc95,0xbd6d3cc4,0x3c95bd75,0x3d0e3d55,0xbd7fbbc9,0x3d800000,0xbd223d46,0xbc48bd7b,0x3d623cf1,
0xbd800000,0x3d46bd22,0xbc483d7b,0xbcf1bd62,0x3d6d3cc4,0xbd753c95,0x3d0ebd55,0x3bc93d7f,0xbd35bd35,0x3d7f3bc9,0xbd553d0e,0x3c95bd75,0x3cc43d6d,0xbd62bcf1,0x3d7bbc48,0xbd223d46,
0x3d80,0xbd22bd46,0x3d7b3c48,0xbd623cf1,0x3cc4bd6d,0x3c953d75,0xbd55bd0e,0x3d7fbbc9,0xbd353d35,0x3bc9bd7f,0x3d0e3d55,0xbd75bc95,0x3d6dbcc4,0xbcf13d62,0xbc48bd7b,0x3d463d22,
0xbcc4bd6d,0x3d463d22,0xbd7bbc48,0x3d75bc95,0x3d800000,0xbd623cf1,0x3d0ebd55,0xbbc93d7f,0x3d6d3cc4,0xbd7f3bc9,0x3d55bd0e,0xbcf13d62,0xbd353d35,0x3c95bd75,0x3c483d7b,0xbd22bd46,
0x3d6dbcc4,0xbd223d46,0x3c48bd7b,0x3c953d75,0x3d80,0xbcf1bd62,0x3d553d0e,0xbd7fbbc9,0xbcc43d6d,0xbbc9bd7f,0x3d0e3d55,0xbd62bcf1,0xbd35bd35,0x3d753c95,0xbd7b3c48,0x3d46bd22,
0x3d353d35,0xbd62bcf1,0x3d7b3c48,0xbd7f3bc9,0x3d6dbcc4,0xbd463d22,0x3d0ebd55,0xbc953d75,0xbd800000,0x3d75bc95,0xbd553d0e,0x3d22bd46,0xbcc43d6d,0x3bc9bd7f,0x3c483d7b,0xbcf1bd62,
0x3d35bd35,0xbcf13d62,0x3c48bd7b,0x3bc93d7f,0xbcc4bd6d,0x3d223d46,0xbd55bd0e,0x3d753c95,0x3d80,0xbc95bd75,0x3d0e3d55,0xbd46bd22,0x3d6d3cc4,0xbd7fbbc9,0x3d7bbc48,0xbd623cf1,
0x3cc4bd6d,0xbc953d75,0x3c48bd7b,0xbbc93d7f,0x3d35bd35,0xbd223d46,0x3d0ebd55,0xbcf13d62,0x3d6dbcc4,0xbd623cf1,0x3d55bd0e,0xbd463d22,0x3d800000,0xbd7f3bc9,0x3d7bbc48,0xbd753c95,
0x3d6d3cc4,0xbd75bc95,0x3d7b3c48,0xbd7fbbc9,0x3d353d35,0xbd46bd22,0x3d553d0e,0xbd62bcf1,0x3cc43d6d,0xbcf1bd62,0x3d0e3d55,0xbd22bd46,0x3d80,0xbbc9bd7f,0x3c483d7b,0xbc95bd75,
0xbd800000,0x3bc9bd7f,0x3d7b3c48,0xbc953d75,0xbd6dbcc4,0x3cf1bd62,0x3d553d0e,0xbd223d46,0xbd35bd35,0x3d46bd22,0x3d0e3d55,0xbd623cf1,0xbcc4bd6d,0x3d75bc95,0x3c483d7b,0xbd7f3bc9,
0x8000bd80,0x3d7f3bc9,0xbc483d7b,0xbd75bc95,0x3cc4bd6d,0x3d623cf1,0xbd0e3d55,0xbd46bd22,0x3d35bd35,0x3d223d46,0xbd553d0e,0xbcf1bd62,0x3d6dbcc4,0x3c953d75,0xbd7b3c48,0xbbc9bd7f,
0xbcc4bd6d,0x3d7fbbc9,0xbc483d7b,0xbd62bcf1,0xbd800000,0x3c95bd75,0x3d553d0e,0xbd463d22,0x3d6d3cc4,0xbd223d46,0xbd0ebd55,0x3d75bc95,0x3d35bd35,0x3cf13d62,0xbd7b3c48,0x3bc9bd7f,
0xbd6d3cc4,0xbbc9bd7f,0x3d7b3c48,0xbcf13d62,0x80003d80,0xbd75bc95,0x3d0ebd55,0x3d223d46,0x3cc4bd6d,0x3d463d22,0xbd553d0e,0xbc95bd75,0xbd35bd35,0x3d62bcf1,0x3c483d7b,0xbd7fbbc9,
0x3d353d35,0xbd753c95,0x3c48bd7b,0x3d463d22,0xbd6d3cc4,0x3bc9bd7f,0x3d553d0e,0xbd623cf1,0xbd800000,0x3cf1bd62,0x3d0e3d55,0xbd7f3bc9,0x3cc4bd6d,0x3d223d46,0xbd7b3c48,0x3c95bd75,
0xbd353d35,0xbc95bd75,0x3d7b3c48,0xbd223d46,0xbcc4bd6d,0x3d7f3bc9,0xbd0e3d55,0xbcf1bd62,0x8000bd80,0x3d623cf1,0xbd553d0e,0xbbc9bd7f,0x3d6d3cc4,0xbd463d22,0xbc48bd7b,0x3d753c95,
0x3cc4bd6d,0x3cf13d62,0xbd7bbc48,0x3d46bd22,0xbd353d35,0xbbc9bd7f,0x3d553d0e,0xbd753c95,0x3d6dbcc4,0xbc953d75,0xbd0ebd55,0x3d7f3bc9,0xbd800000,0x3d22bd46,0x3c483d7b,0xbd62bcf1,
0xbd6dbcc4,0x3d62bcf1,0xbc483d7b,0xbd22bd46,0x3d353d35,0xbd7f3bc9,0x3d0ebd55,0x3c953d75,0xbcc4bd6d,0x3d753c95,0xbd553d0e,0x3bc9bd7f,0x80003d80,0xbd46bd22,0x3d7bbc48,0xbcf13d62,
0x8000bd80,0x3d223d46,0xbd7bbc48,0x3d62bcf1,0xbcc43d6d,0xbc95bd75,0x3d553d0e,0xbd7f3bc9,0x3d35bd35,0xbbc93d7f,0xbd0ebd55,0x3d753c95,0xbd6d3cc4,0x3cf1bd62,0x3c483d7b,0xbd46bd22,
0xbd800000,0x3d46bd22,0xbc483d7b,0xbcf1bd62,0x3d6d3cc4,0xbd753c95,0x3d0ebd55,0x3bc93d7f,0xbd35bd35,0x3d7f3bc9,0xbd553d0e,0x3c95bd75,0x3cc43d6d,0xbd62bcf1,0x3d7bbc48,0xbd223d46,
0x3d6dbcc4,0xbd223d46,0x3c48bd7b,0x3c953d75,0x80003d80,0xbcf1bd62,0x3d553d0e,0xbd7fbbc9,0xbcc43d6d,0xbbc9bd7f,0x3d0e3d55,0xbd62bcf1,0xbd35bd35,0x3d753c95,0xbd7b3c48,0x3d46bd22,
0x3cc43d6d,0xbd46bd22,0x3d7b3c48,0xbd753c95,0xbd800000,0x3d62bcf1,0xbd0e3d55,0x3bc9bd7f,0xbd6dbcc4,0x3d7fbbc9,0xbd553d0e,0x3cf1bd62,0x3d35bd35,0xbc953d75,0xbc48bd7b,0x3d223d46,
0xbd353d35,0x3cf1bd62,0xbc483d7b,0xbbc9bd7f,0x3cc43d6d,0xbd22bd46,0x3d553d0e,0xbd75bc95,0x8000bd80,0x3c953d75,0xbd0ebd55,0x3d463d22,0xbd6dbcc4,0x3d7f3bc9,0xbd7b3c48,0x3d62bcf1,
0x3d353d35,0xbd62bcf1,0x3d7b3c48,0xbd7f3bc9,0x3d6dbcc4,0xbd463d22,0x3d0ebd55,0xbc953d75,0xbd800000,0x3d75bc95,0xbd553d0e,0x3d22bd46,0xbcc43d6d,0x3bc9bd7f,0x3c483d7b,0xbcf1bd62,
0x3d6d3cc4,0xbd75bc95,0x3d7b3c48,0xbd7fbbc9,0x3d353d35,0xbd46bd22,0x3d553d0e,0xbd62bcf1,0x3cc43d6d,0xbcf1bd62,0x3d0e3d55,0xbd22bd46,0x80003d80,0xbbc9bd7f,0x3c483d7b,0xbc95bd75,
0xbcc43d6d,0x3c95bd75,0xbc483d7b,0x3bc9bd7f,0xbd353d35,0x3d22bd46,0xbd0e3d55,0x3cf1bd62,0xbd6d3cc4,0x3d62bcf1,0xbd553d0e,0x3d46bd22,0xbd800000,0x3d7fbbc9,0xbd7b3c48,0x3d75bc95,
0x3d80,0x3bc9bd7f,0xbc483d7b,0x3c95bd75,0xbcc43d6d,0x3cf1bd62,0xbd0e3d55,0x3d22bd46,0xbd353d35,0x3d46bd22,0xbd553d0e,0x3d62bcf1,0xbd6d3cc4,0x3d75bc95,0xbd7b3c48,0x3d7fbbc9,
0xbd800000,0x3d7f3bc9,0xbd7bbc48,0x3d753c95,0xbd6dbcc4,0x3d623cf1,0xbd55bd0e,0x3d463d22,0xbd35bd35,0x3d223d46,0xbd0ebd55,0x3cf13d62,0xbcc4bd6d,0x3c953d75,0xbc48bd7b,0x3bc93d7f,
0xbd6d3cc4,0x3d7fbbc9,0xbd7bbc48,0x3d623cf1,0x3d80,0x3c95bd75,0xbd0e3d55,0x3d46bd22,0x3cc4bd6d,0xbd223d46,0x3d55bd0e,0xbd753c95,0xbd35bd35,0x3cf13d62,0xbc48bd7b,0xbbc93d7f,
0x3cc43d6d,0xbbc9bd7f,0xbc483d7b,0x3cf1bd62,0x3d800000,0xbd75bc95,0x3d553d0e,0xbd22bd46,0xbd6dbcc4,0x3d463d22,0xbd0ebd55,0x3c953d75,0xbd353d35,0x3d62bcf1,0xbd7b3c48,0x3d7f3bc9,
0x3d35bd35,0xbd753c95,0x3d7b3c48,0xbd46bd22,0x3cc43d6d,0x3bc9bd7f,0xbd0e3d55,0x3d62bcf1,0x3d80,0x3cf1bd62,0xbd553d0e,0x3d7fbbc9,0xbd6dbcc4,0x3d223d46,0xbc48bd7b,0xbc953d75,
0x3d353d35,0xbc95bd75,0xbc483d7b,0x3d22bd46,0xbd6d3cc4,0x3d7f3bc9,0xbd55bd0e,0x3cf13d62,0xbd800000,0x3d623cf1,0xbd0ebd55,0x3bc93d7f,0x3cc4bd6d,0xbd463d22,0x3d7bbc48,0xbd75bc95,
0xbd6dbcc4,0x3cf13d62,0x3c48bd7b,0xbd463d22,0x3d353d35,0xbbc9bd7f,0xbd0e3d55,0x3d75bc95,0xbcc4bd6d,0xbc953d75,0x3d55bd0e,0xbd7fbbc9,0x3d80,0x3d22bd46,0xbd7b3c48,0x3d623cf1,
0xbcc43d6d,0x3d62bcf1,0xbd7bbc48,0x3d223d46,0x3d35bd35,0xbd7f3bc9,0x3d553d0e,0xbc95bd75,0xbd6d3cc4,0x3d753c95,0xbd0ebd55,0xbbc93d7f,0x3d800000,0xbd46bd22,0x3c483d7b,0x3cf1bd62,
0xbd800000,0x3d223d46,0x3c48bd7b,0xbd623cf1,0x3d6d3cc4,0xbc95bd75,0xbd0e3d55,0x3d7fbbc9,0xbd35bd35,0xbbc93d7f,0x3d55bd0e,0xbd75bc95,0x3cc43d6d,0x3cf1bd62,0xbd7b3c48,0x3d463d22,
0x3d80,0x3d46bd22,0xbd7bbc48,0x3cf13d62,0x3cc4bd6d,0xbd753c95,0x3d553d0e,0xbbc9bd7f,0xbd353d35,0x3d7f3bc9,0xbd0ebd55,0xbc953d75,0x3d6dbcc4,0xbd62bcf1,0x3c483d7b,0x3d22bd46,
0xbcc4bd6d,0xbd223d46,0x3d7b3c48,0xbc95bd75,0x3d800000,0xbcf1bd62,0xbd0e3d55,0x3d7f3bc9,0x3d6d3cc4,0xbbc9bd7f,0xbd553d0e,0x3d623cf1,0xbd353d35,0x3d753c95,0xbc48bd7b,0xbd463d22,
0x3d6dbcc4,0xbd46bd22,0xbc483d7b,0x3d75bc95,0x3d80,0x3d62bcf1,0xbd55bd0e,0xbbc93d7f,0xbcc43d6d,0x3d7fbbc9,0xbd0ebd55,0xbcf13d62,0xbd35bd35,0xbc953d75,0x3d7bbc48,0xbd22bd46,
0x3d353d35,0x3cf1bd62,0xbd7bbc48,0x3bc93d7f,0x3d6dbcc4,0xbd22bd46,0xbd0e3d55,0x3d753c95,0xbd800000,0x3c953d75,0x3d55bd0e,0xbd46bd22,0xbcc43d6d,0x3d7f3bc9,0xbc48bd7b,0xbd623cf1,
0x3d35bd35,0xbd62bcf1,0xbc483d7b,0x3d7fbbc9,0xbcc4bd6d,0xbd463d22,0x3d553d0e,0x3c95bd75,0x3d80,0x3d75bc95,0xbd0ebd55,0xbd223d46,0x3d6d3cc4,0x3bc9bd7f,0xbd7b3c48,0x3cf13d62,
0x3cc4bd6d,0xbd75bc95,0xbc483d7b,0x3d7f3bc9,0x3d35bd35,0xbd46bd22,0xbd0e3d55,0x3d623cf1,0x3d6dbcc4,0xbcf1bd62,0xbd553d0e,0x3d223d46,0x3d800000,0xbbc9bd7f,0xbd7b3c48,0x3c953d75,
0x3d6d3cc4,0x3c95bd75,0xbd7bbc48,0xbbc93d7f,0x3d353d35,0x3d22bd46,0xbd55bd0e,0xbcf13d62,0x3cc43d6d,0x3d62bcf1,0xbd0ebd55,0xbd463d22,0x3d80,0x3d7fbbc9,0xbc48bd7b,0xbd753c95,
0xbd800000,0x3d7f3bc9,0xbd7bbc48,0x3d753c95,0xbd6dbcc4,0x3d623cf1,0xbd55bd0e,0x3d463d22,0xbd35bd35,0x3d223d46,0xbd0ebd55,0x3cf13d62,0xbcc4bd6d,0x3c953d75,0xbc48bd7b,0x3bc93d7f,
0x8000bd80,0xbbc93d7f,0x3c48bd7b,0xbc953d75,0x3cc4bd6d,0xbcf13d62,0x3d0ebd55,0xbd223d46,0x3d35bd35,0xbd463d22,0x3d55bd0e,0xbd623cf1,0x3d6dbcc4,0xbd753c95,0x3d7bbc48,0xbd7f3bc9,
0xbcc4bd6d,0x3bc93d7f,0x3c48bd7b,0xbcf13d62,0xbd800000,0x3d753c95,0xbd55bd0e,0x3d223d46,0x3d6d3cc4,0xbd46bd22,0x3d0e3d55,0xbc95bd75,0x3d35bd35,0xbd623cf1,0x3d7bbc48,0xbd7fbbc9,
0xbd6d3cc4,0x3d7fbbc9,0xbd7bbc48,0x3d623cf1,0x80003d80,0x3c95bd75,0xbd0e3d55,0x3d46bd22,0x3cc4bd6d,0xbd223d46,0x3d55bd0e,0xbd753c95,0xbd35bd35,0x3cf13d62,0xbc48bd7b,0xbbc93d7f,
0x3d353d35,0xbc95bd75,0xbc483d7b,0x3d22bd46,0xbd6d3cc4,0x3d7f3bc9,0xbd55bd0e,0x3cf13d62,0xbd800000,0x3d623cf1,0xbd0ebd55,0x3bc93d7f,0x3cc4bd6d,0xbd463d22,0x3d7bbc48,0xbd75bc95,
0xbd353d35,0x3d75bc95,0xbd7bbc48,0x3d463d22,0xbcc4bd6d,0xbbc93d7f,0x3d0ebd55,0xbd623cf1,0x8000bd80,0xbcf13d62,0x3d55bd0e,0xbd7f3bc9,0x3d6d3cc4,0xbd22bd46,0x3c483d7b,0x3c95bd75,
0x3cc4bd6d,0xbd623cf1,0x3d7b3c48,0xbd22bd46,0xbd353d35,0x3d7fbbc9,0xbd55bd0e,0x3c953d75,0x3d6dbcc4,0xbd75bc95,0x3d0e3d55,0x3bc9bd7f,0xbd800000,0x3d463d22,0xbc48bd7b,0xbcf13d62,
0xbd6dbcc4,0x3cf13d62,0x3c48bd7b,0xbd463d22,0x3d353d35,0xbbc9bd7f,0xbd0e3d55,0x3d75bc95,0xbcc4bd6d,0xbc953d75,0x3d55bd0e,0xbd7fbbc9,0x80003d80,0x3d22bd46,0xbd7b3c48,0x3d623cf1,
0x8000bd80,0xbd463d22,0x3d7b3c48,0xbcf1bd62,0xbcc43d6d,0x3d75bc95,0xbd55bd0e,0x3bc93d7f,0x3d35bd35,0xbd7fbbc9,0x3d0e3d55,0x3c95bd75,0xbd6d3cc4,0x3d623cf1,0xbc48bd7b,0xbd223d46,
0xbd800000,0x3d223d46,0x3c48bd7b,0xbd623cf1,0x3d6d3cc4,0xbc95bd75,0xbd0e3d55,0x3d7fbbc9,0xbd35bd35,0xbbc93d7f,0x3d55bd0e,0xbd75bc95,0x3cc43d6d,0x3cf1bd62,0xbd7b3c48,0x3d463d22,
0x3d6dbcc4,0xbd46bd22,0xbc483d7b,0x3d75bc95,0x80003d80,0x3d62bcf1,0xbd55bd0e,0xbbc93d7f,0xbcc43d6d,0x3d7fbbc9,0xbd0ebd55,0xbcf13d62,0xbd35bd35,0xbc953d75,0x3d7bbc48,0xbd22bd46,
0x3cc43d6d,0x3d22bd46,0xbd7bbc48,0x3c953d75,0xbd800000,0x3cf13d62,0x3d0ebd55,0xbd7fbbc9,0xbd6dbcc4,0x3bc93d7f,0x3d55bd0e,0xbd62bcf1,0x3d35bd35,0xbd75bc95,0x3c483d7b,0x3d46bd22,
0xbd353d35,0x3d623cf1,0x3c48bd7b,0xbd7f3bc9,0x3cc43d6d,0x3d46bd22,0xbd55bd0e,0xbc953d75,0x8000bd80,0xbd753c95,0x3d0e3d55,0x3d22bd46,0xbd6dbcc4,0xbbc93d7f,0x3d7bbc48,0xbcf1bd62,
0x3d353d35,0x3cf1bd62,0xbd7bbc48,0x3bc93d7f,0x3d6dbcc4,0xbd22bd46,0xbd0e3d55,0x3d753c95,0xbd800000,0x3c953d75,0x3d55bd0e,0xbd46bd22,0xbcc43d6d,0x3d7f3bc9,0xbc48bd7b,0xbd623cf1,
0x3d6d3cc4,0x3c95bd75,0xbd7bbc48,0xbbc93d7f,0x3d353d35,0x3d22bd46,0xbd55bd0e,0xbcf13d62,0x3cc43d6d,0x3d62bcf1,0xbd0ebd55,0xbd463d22,0x80003d80,0x3d7fbbc9,0xbc48bd7b,0xbd753c95,
0xbcc43d6d,0x3d753c95,0x3c48bd7b,0xbd7fbbc9,0xbd353d35,0x3d463d22,0x3d0ebd55,0xbd62bcf1,0xbd6d3cc4,0x3cf13d62,0x3d55bd0e,0xbd22bd46,0xbd800000,0x3bc93d7f,0x3d7bbc48,0xbc95bd75,
0x3d80,0x3d7f3bc9,0x3c48bd7b,0xbd75bc95,0xbcc43d6d,0x3d623cf1,0x3d0ebd55,0xbd46bd22,0xbd353d35,0x3d223d46,0x3d55bd0e,0xbcf1bd62,0xbd6d3cc4,0x3c953d75,0x3d7bbc48,0xbbc9bd7f,
0xbd800000,0xbbc93d7f,0x3d7b3c48,0x3c95bd75,0xbd6dbcc4,0xbcf13d62,0x3d553d0e,0x3d22bd46,0xbd35bd35,0xbd463d22,0x3d0e3d55,0x3d62bcf1,0xbcc4bd6d,0xbd753c95,0x3c483d7b,0x3d7fbbc9,
0xbd6d3cc4,0x3bc93d7f,0x3d7b3c48,0x3cf1bd62,0x3d80,0x3d753c95,0x3d0ebd55,0xbd22bd46,0x3cc4bd6d,0xbd46bd22,0xbd553d0e,0x3c953d75,0xbd35bd35,0xbd623cf1,0x3c483d7b,0x3d7f3bc9,
0x3cc43d6d,0x3d7fbbc9,0x3c48bd7b,0xbd62bcf1,0x3d800000,0x3c95bd75,0xbd55bd0e,0xbd463d22,0xbd6dbcc4,0xbd223d46,0x3d0e3d55,0x3d75bc95,0xbd353d35,0x3cf13d62,0x3d7bbc48,0x3bc9bd7f,
0x3d35bd35,0xbc95bd75,0xbd7bbc48,0xbd223d46,0x3cc43d6d,0x3d7f3bc9,0x3d0ebd55,0xbcf1bd62,0x3d80,0x3d623cf1,0x3d55bd0e,0xbbc9bd7f,0xbd6dbcc4,0xbd463d22,0x3c483d7b,0x3d753c95,
0x3d353d35,0x3d75bc95,0x3c48bd7b,0xbd46bd22,0xbd6d3cc4,0xbbc93d7f,0x3d553d0e,0x3d62bcf1,0xbd800000,0xbcf13d62,0x3d0e3d55,0x3d7fbbc9,0x3cc4bd6d,0xbd22bd46,0xbd7b3c48,0xbc953d75,
0xbd6dbcc4,0xbd623cf1,0xbc483d7b,0x3d223d46,0x3d353d35,0x3d7fbbc9,0x3d0ebd55,0xbc95bd75,0xbcc4bd6d,0xbd75bc95,0xbd553d0e,0xbbc93d7f,0x3d80,0x3d463d22,0x3d7bbc48,0x3cf1bd62,
0xbcc43d6d,0x3cf13d62,0x3d7b3c48,0x3d46bd22,0x3d35bd35,0xbbc9bd7f,0xbd55bd0e,0xbd753c95,0xbd6d3cc4,0xbc953d75,0x3d0e3d55,0x3d7f3bc9,0x3d800000,0x3d22bd46,0xbc48bd7b,0xbd62bcf1,
0xbd800000,0xbd463d22,0xbc483d7b,0x3cf13d62,0x3d6d3cc4,0x3d75bc95,0x3d0ebd55,0xbbc9bd7f,0xbd35bd35,0xbd7fbbc9,0xbd553d0e,0xbc953d75,0x3cc43d6d,0x3d623cf1,0x3d7bbc48,0x3d22bd46,
0x3d80,0x3d223d46,0x3d7b3c48,0x3d62bcf1,0x3cc4bd6d,0xbc95bd75,0xbd55bd0e,0xbd7f3bc9,0xbd353d35,0xbbc93d7f,0x3d0e3d55,0x3d753c95,0x3d6dbcc4,0x3cf1bd62,0xbc48bd7b,0xbd46bd22,
0xbcc4bd6d,0xbd46bd22,0xbd7bbc48,0xbd753c95,0x3d800000,0x3d62bcf1,0x3d0ebd55,0x3bc9bd7f,0x3d6d3cc4,0x3d7fbbc9,0x3d55bd0e,0x3cf1bd62,0xbd353d35,0xbc953d75,0x3c483d7b,0x3d223d46,
0x3d6dbcc4,0x3d22bd46,0x3c48bd7b,0xbc95bd75,0x3d80,0x3cf13d62,0x3d553d0e,0x3d7f3bc9,0xbcc43d6d,0x3bc93d7f,0x3d0e3d55,0x3d623cf1,0xbd35bd35,0xbd75bc95,0xbd7b3c48,0xbd463d22,
0x3d353d35,0x3d623cf1,0x3d7b3c48,0x3d7fbbc9,0x3d6dbcc4,0x3d46bd22,0x3d0ebd55,0x3c95bd75,0xbd800000,0xbd753c95,0xbd553d0e,0xbd223d46,0xbcc43d6d,0xbbc93d7f,0x3c483d7b,0x3cf13d62,
0x3d35bd35,0x3cf1bd62,0x3c48bd7b,0xbbc9bd7f,0xbcc4bd6d,0xbd22bd46,0xbd55bd0e,0xbd75bc95,0x3d80,0x3c953d75,0x3d0e3d55,0x3d463d22,0x3d6d3cc4,0x3d7f3bc9,0x3d7bbc48,0x3d62bcf1,
0x3cc4bd6d,0x3c95bd75,0x3c48bd7b,0x3bc9bd7f,0x3d35bd35,0x3d22bd46,0x3d0ebd55,0x3cf1bd62,0x3d6dbcc4,0x3d62bcf1,0x3d55bd0e,0x3d46bd22,0x3d800000,0x3d7fbbc9,0x3d7bbc48,0x3d75bc95,
0x3d6d3cc4,0x3d753c95,0x3d7b3c48,0x3d7f3bc9,0x3d353d35,0x3d463d22,0x3d553d0e,0x3d623cf1,0x3cc43d6d,0x3cf13d62,0x3d0e3d55,0x3d223d46,0x3d80,0x3bc93d7f,0x3c483d7b,0x3c953d75,
0xbd800000,0xbbc93d7f,0x3d7b3c48,0x3c95bd75,0xbd6dbcc4,0xbcf13d62,0x3d553d0e,0x3d22bd46,0xbd35bd35,0xbd463d22,0x3d0e3d55,0x3d62bcf1,0xbcc4bd6d,0xbd753c95,0x3c483d7b,0x3d7fbbc9,
0x8000bd80,0xbd7fbbc9,0xbc483d7b,0x3d753c95,0x3cc4bd6d,0xbd62bcf1,0xbd0e3d55,0x3d463d22,0x3d35bd35,0xbd22bd46,0xbd553d0e,0x3cf13d62,0x3d6dbcc4,0xbc95bd75,0xbd7b3c48,0x3bc93d7f,
0xbcc4bd6d,0xbd7f3bc9,0xbc483d7b,0x3d623cf1,0xbd800000,0xbc953d75,0x3d553d0e,0x3d46bd22,0x3d6d3cc4,0x3d22bd46,0xbd0ebd55,0xbd753c95,0x3d35bd35,0xbcf1bd62,0xbd7b3c48,0xbbc93d7f,
0xbd6d3cc4,0x3bc93d7f,0x3d7b3c48,0x3cf1bd62,0x80003d80,0x3d753c95,0x3d0ebd55,0xbd22bd46,0x3cc4bd6d,0xbd46bd22,0xbd553d0e,0x3c953d75,0xbd35bd35,0xbd623cf1,0x3c483d7b,0x3d7f3bc9,
0x3d353d35,0x3d75bc95,0x3c48bd7b,0xbd46bd22,0xbd6d3cc4,0xbbc93d7f,0x3d553d0e,0x3d62bcf1,0xbd800000,0xbcf13d62,0x3d0e3d55,0x3d7fbbc9,0x3cc4bd6d,0xbd22bd46,0xbd7b3c48,0xbc953d75,
0xbd353d35,0x3c953d75,0x3d7b3c48,0x3d22bd46,0xbcc4bd6d,0xbd7fbbc9,0xbd0e3d55,0x3cf13d62,0x8000bd80,0xbd62bcf1,0xbd553d0e,0x3bc93d7f,0x3d6d3cc4,0x3d46bd22,0xbc48bd7b,0xbd75bc95,
0x3cc4bd6d,0xbcf1bd62,0xbd7bbc48,0xbd463d22,0xbd353d35,0x3bc93d7f,0x3d553d0e,0x3d75bc95,0x3d6dbcc4,0x3c95bd75,0xbd0ebd55,0xbd7fbbc9,0xbd800000,0xbd223d46,0x3c483d7b,0x3d623cf1,
0xbd6dbcc4,0xbd623cf1,0xbc483d7b,0x3d223d46,0x3d353d35,0x3d7fbbc9,0x3d0ebd55,0xbc95bd75,0xbcc4bd6d,0xbd75bc95,0xbd553d0e,0xbbc93d7f,0x80003d80,0x3d463d22,0x3d7bbc48,0x3cf1bd62,
0x8000bd80,0xbd22bd46,0xbd7bbc48,0xbd623cf1,0xbcc43d6d,0x3c953d75,0x3d553d0e,0x3d7fbbc9,0x3d35bd35,0x3bc9bd7f,0xbd0ebd55,0xbd75bc95,0xbd6d3cc4,0xbcf13d62,0x3c483d7b,0x3d463d22,
0xbd800000,0xbd463d22,0xbc483d7b,0x3cf13d62,0x3d6d3cc4,0x3d75bc95,0x3d0ebd55,0xbbc9bd7f,0xbd35bd35,0xbd7fbbc9,0xbd553d0e,0xbc953d75,0x3cc43d6d,0x3d623cf1,0x3d7bbc48,0x3d22bd46,
0x3d6dbcc4,0x3d22bd46,0x3c48bd7b,0xbc95bd75,0x80003d80,0x3cf13d62,0x3d553d0e,0x3d7f3bc9,0xbcc43d6d,0x3bc93d7f,0x3d0e3d55,0x3d623cf1,0xbd35bd35,0xbd75bc95,0xbd7b3c48,0xbd463d22,
0x3cc43d6d,0x3d463d22,0x3d7b3c48,0x3d75bc95,0xbd800000,0xbd623cf1,0xbd0e3d55,0xbbc93d7f,0xbd6dbcc4,0xbd7f3bc9,0xbd553d0e,0xbcf13d62,0x3d35bd35,0x3c95bd75,0xbc48bd7b,0xbd22bd46,
0xbd353d35,0xbcf13d62,0xbc483d7b,0x3bc93d7f,0x3cc43d6d,0x3d223d46,0x3d553d0e,0x3d753c95,0x8000bd80,0xbc95bd75,0xbd0ebd55,0xbd46bd22,0xbd6dbcc4,0xbd7fbbc9,0xbd7b3c48,0xbd623cf1,
0x3d353d35,0x3d623cf1,0x3d7b3c48,0x3d7fbbc9,0x3d6dbcc4,0x3d46bd22,0x3d0ebd55,0x3c95bd75,0xbd800000,0xbd753c95,0xbd553d0e,0xbd223d46,0xbcc43d6d,0xbbc93d7f,0x3c483d7b,0x3cf13d62,
0x3d6d3cc4,0x3d753c95,0x3d7b3c48,0x3d7f3bc9,0x3d353d35,0x3d463d22,0x3d553d0e,0x3d623cf1,0x3cc43d6d,0x3cf13d62,0x3d0e3d55,0x3d223d46,0x80003d80,0x3bc93d7f,0x3c483d7b,0x3c953d75,
0xbcc43d6d,0xbc953d75,0xbc483d7b,0xbbc93d7f,0xbd353d35,0xbd223d46,0xbd0e3d55,0xbcf13d62,0xbd6d3cc4,0xbd623cf1,0xbd553d0e,0xbd463d22,0xbd800000,0xbd7f3bc9,0xbd7b3c48,0xbd753c95,
0x3d80,0xbc163d7d,0xbc953d75,0xbcdb3d67,0xbd0e3d55,0xbd2c3d3e,0xbd463d22,0xbd5c3d04,0xbd6d3cc4,0xbd783c79,0xbd7f3bc9,0xbd80bb49,0xbd7bbc48,0xbd71bcac,0xbd62bcf1,0xbd4ebd18,
0xbd35bd35,0xbd18bd4e,0xbcf1bd62,0xbcacbd71,0xbc48bd7b,0xbb49bd80,0x3bc9bd7f,0x3c79bd78,0x3cc4bd6d,0x3d04bd5c,0x3d22bd46,0x3d3ebd2c,0x3d55bd0e,0x3d67bcdb,0x3d75bc95,0x3d7dbc16,
0xbd7b3c48,0xbd7dbc16,0xbd62bcf1,0xbd2cbd3e,0x3d80,0xbcac3d71,0xbd223d46,0xbd5c3d04,0x3d55bd0e,0x3d78bc79,0x3d7f3bc9,0x3d673cdb,0xbcc4bd6d,0xbb49bd80,0x3c95bd75,0x3d18bd4e,
0xbd0e3d55,0xbd4e3d18,0xbd753c95,0xbd80bb49,0x3d353d35,0x3cdb3d67,0x3bc93d7f,0xbc793d78,0x3c48bd7b,0x3d04bd5c,0x3d46bd22,0x3d71bcac,0xbd6dbcc4,0xbd3ebd2c,0xbcf1bd62,0xbc16bd7d,
0x3d6dbcc4,0x3d7d3c16,0x3d463d22,0x3cac3d71,0xbc483d7b,0xbd2c3d3e,0xbd753c95,0xbd78bc79,0x3d80,0xbd043d5c,0xbd623cf1,0xbd80bb49,0xbd55bd0e,0xbcdbbd67,0x3bc9bd7f,0x3d18bd4e,
0xbcc43d6d,0xbd4e3d18,0xbd7f3bc9,0xbd67bcdb,0xbd0ebd55,0xbb49bd80,0x3cf1bd62,0x3d5cbd04,0xbd35bd35,0xbc79bd78,0x3c95bd75,0x3d3ebd2c,0x3d7bbc48,0x3d713cac,0x3d223d46,0x3c163d7d,
0xbd0ebd55,0x3c16bd7d,0x3d46bd22,0x3d803b49,0x3cc43d6d,0xbcac3d71,0xbd623cf1,0xbd78bc79,0xbc48bd7b,0x3d04bd5c,0x3d75bc95,0x3d673cdb,0x3d80,0xbd2c3d3e,0xbd7f3bc9,0xbd4ebd18,
0xbd7bbc48,0xbd18bd4e,0x3bc9bd7f,0x3d3ebd2c,0x3d6d3cc4,0x3cdb3d67,0xbc953d75,0xbd5c3d04,0xbd55bd0e,0xbc79bd78,0x3cf1bd62,0x3d71bcac,0x3d353d35,0x3b493d80,0xbd223d46,0xbd7d3c16,
0xbd35bd35,0x3c16bd7d,0x3d62bcf1,0x3d673cdb,0x3c483d7b,0xbd2c3d3e,0xbd7fbbc9,0xbd04bd5c,0x3cc4bd6d,0x3d78bc79,0x3d463d22,0xbb493d80,0xbd553d0e,0xbd71bcac,0xbc95bd75,0x3d18bd4e,
0x3d80,0xbd4e3d18,0xbd75bc95,0xbcacbd71,0x3d0ebd55,0x3d80bb49,0x3d223d46,0xbc793d78,0xbd6d3cc4,0xbd5cbd04,0xbbc9bd7f,0x3d3ebd2c,0x3d7b3c48,0x3cdb3d67,0xbcf13d62,0xbd7d3c16,
0x3d0ebd55,0x3d7d3c16,0x3c953d75,0xbd3e3d2c,0x3d353d35,0xbcac3d71,0xbd7f3bc9,0xbd04bd5c,0xbc483d7b,0xbd783c79,0xbd22bd46,0x3cdbbd67,0xbd6dbcc4,0xbb49bd80,0x3d62bcf1,0x3d4e3d18,
0x3d7bbc48,0x3d183d4e,0xbcf13d62,0xbd80bb49,0x3d80,0xbd673cdb,0xbd46bd22,0x3c79bd78,0xbd553d0e,0xbd5cbd04,0x3bc9bd7f,0x3d71bcac,0xbcc4bd6d,0x3d2cbd3e,0x3d753c95,0x3c163d7d,
0xbcc43d6d,0xbd7dbc16,0xbbc9bd7f,0x3d71bcac,0x3d0e3d55,0xbd2c3d3e,0xbd62bcf1,0x3c79bd78,0xbd35bd35,0x3d04bd5c,0x3d753c95,0xbb493d80,0xbd7b3c48,0xbcdbbd67,0x3d46bd22,0x3d4e3d18,
0x3d6dbcc4,0x3d183d4e,0xbd223d46,0xbd67bcdb,0x3c48bd7b,0x3d80bb49,0x3c953d75,0xbd5c3d04,0x3d80,0xbd783c79,0xbcf1bd62,0x3d3ebd2c,0x3d553d0e,0xbcac3d71,0xbd7fbbc9,0xbc16bd7d,
0x3d7b3c48,0xbc163d7d,0xbd7fbbc9,0x3b49bd80,0x3d6d3cc4,0xbcac3d71,0xbd75bc95,0x3c79bd78,0x3d553d0e,0xbd043d5c,0xbd62bcf1,0x3cdbbd67,0x3d353d35,0xbd2c3d3e,0xbd46bd22,0x3d18bd4e,
0x3d0e3d55,0xbd4e3d18,0xbd22bd46,0x3d3ebd2c,0x3cc43d6d,0xbd673cdb,0xbcf1bd62,0x3d5cbd04,0x3c483d7b,0xbd783c79,0xbc95bd75,0x3d71bcac,0x3d80,0xbd803b49,0xbbc9bd7f,0x3d7dbc16,
0xbd800000,0xbd7dbc16,0xbd75bc95,0xbd67bcdb,0xbd55bd0e,0xbd3ebd2c,0xbd22bd46,0xbd04bd5c,0xbcc4bd6d,0xbc79bd78,0xbbc9bd7f,0x3b49bd80,0x3c48bd7b,0x3cacbd71,0x3cf1bd62,0x3d18bd4e,
0x3d35bd35,0x3d4ebd18,0x3d62bcf1,0x3d71bcac,0x3d7bbc48,0x3d80bb49,0x3d7f3bc9,0x3d783c79,0x3d6d3cc4,0x3d5c3d04,0x3d463d22,0x3d2c3d3e,0x3d0e3d55,0x3cdb3d67,0x3c953d75,0x3c163d7d,
0xbc48bd7b,0x3c16bd7d,0x3cf1bd62,0x3d3ebd2c,0xbd800000,0xbd71bcac,0xbd46bd22,0xbd04bd5c,0x3d0e3d55,0x3c793d78,0xbbc93d7f,0xbcdb3d67,0x3d6dbcc4,0x3d80bb49,0x3d753c95,0x3d4e3d18,
0xbd55bd0e,0xbd18bd4e,0xbc95bd75,0x3b49bd80,0xbd353d35,0xbd673cdb,0xbd7f3bc9,0xbd78bc79,0x3d7b3c48,0x3d5c3d04,0x3d223d46,0x3cac3d71,0x3cc4bd6d,0x3d2cbd3e,0x3d62bcf1,0x3d7dbc16,
0x3cc43d6d,0xbc163d7d,0xbd223d46,0xbd713cac,0xbd7bbc48,0xbd3ebd2c,0xbc95bd75,0x3c79bd78,0xbd800000,0xbd5cbd04,0xbcf1bd62,0x3b49bd80,0x3d0ebd55,0x3d67bcdb,0x3d7f3bc9,0x3d4e3d18,
0xbd6dbcc4,0xbd18bd4e,0xbbc9bd7f,0x3cdbbd67,0x3d55bd0e,0x3d80bb49,0x3d623cf1,0x3d043d5c,0x3d35bd35,0x3d78bc79,0x3d753c95,0x3d2c3d3e,0x3c483d7b,0xbcac3d71,0xbd463d22,0xbd7d3c16,
0x3d55bd0e,0x3d7d3c16,0x3d223d46,0xbb493d80,0xbd6d3cc4,0xbd71bcac,0xbcf1bd62,0x3c79bd78,0x3d7bbc48,0x3d5c3d04,0x3c953d75,0xbcdb3d67,0xbd800000,0xbd3ebd2c,0xbbc9bd7f,0x3d18bd4e,
0x3c48bd7b,0x3d4ebd18,0x3d7f3bc9,0x3d2c3d3e,0xbcc43d6d,0xbd673cdb,0xbd75bc95,0xbd04bd5c,0x3d0ebd55,0x3d78bc79,0x3d623cf1,0x3cac3d71,0xbd353d35,0xbd803b49,0xbd46bd22,0xbc16bd7d,
0x3d35bd35,0x3d7d3c16,0x3cf13d62,0xbcdb3d67,0xbd7b3c48,0xbd3ebd2c,0x3bc9bd7f,0x3d5cbd04,0x3d6d3cc4,0x3c793d78,0xbd223d46,0xbd80bb49,0xbd0ebd55,0x3cacbd71,0x3d75bc95,0x3d4e3d18,
0xbd800000,0xbd18bd4e,0x3c95bd75,0x3d71bcac,0x3d553d0e,0x3b493d80,0xbd463d22,0xbd78bc79,0xbcc4bd6d,0x3d04bd5c,0x3d7fbbc9,0x3d2c3d3e,0xbc483d7b,0xbd673cdb,0xbd62bcf1,0xbc16bd7d,
0x3d553d0e,0xbc163d7d,0xbd753c95,0xbd2cbd3e,0xbd353d35,0xbd71bcac,0xbbc9bd7f,0x3d5cbd04,0xbd7bbc48,0xbc79bd78,0x3d46bd22,0x3d673cdb,0x3cc4bd6d,0x3d80bb49,0x3cf13d62,0xbd183d4e,
0x3c483d7b,0xbd4e3d18,0xbd62bcf1,0x3b49bd80,0xbd800000,0xbcdbbd67,0x3d22bd46,0x3d783c79,0xbd0ebd55,0x3d04bd5c,0x3d7f3bc9,0x3cac3d71,0x3d6dbcc4,0x3d3e3d2c,0xbc953d75,0xbd7d3c16,
0xbd6dbcc4,0x3c16bd7d,0x3d7fbbc9,0x3cac3d71,0xbd553d0e,0xbd3ebd2c,0x3cf1bd62,0x3d783c79,0x3d35bd35,0x3d5c3d04,0xbc953d75,0xbd80bb49,0xbc48bd7b,0x3d67bcdb,0x3d223d46,0xbd183d4e,
0x3cc43d6d,0xbd4e3d18,0xbd46bd22,0x3cdbbd67,0x3d7b3c48,0x3b493d80,0xbd753c95,0xbd04bd5c,0xbd800000,0xbc79bd78,0x3d62bcf1,0x3d2c3d3e,0xbd0e3d55,0xbd71bcac,0x3bc9bd7f,0x3d7dbc16,
0xbc483d7b,0xbd7dbc16,0x3bc9bd7f,0x3d803b49,0xbcc43d6d,0xbd71bcac,0x3c95bd75,0x3d783c79,0xbd0e3d55,0xbd5cbd04,0x3cf1bd62,0x3d673cdb,0xbd353d35,0xbd3ebd2c,0x3d22bd46,0x3d4e3d18,
0xbd553d0e,0xbd18bd4e,0x3d46bd22,0x3d2c3d3e,0xbd6d3cc4,0xbcdbbd67,0x3d62bcf1,0x3d043d5c,0xbd7b3c48,0xbc79bd78,0x3d75bc95,0x3cac3d71,0xbd800000,0xbb49bd80,0x3d7fbbc9,0x3c163d7d,
0x3d80,0xbd7dbc16,0x3c95bd75,0x3d673cdb,0xbd0e3d55,0xbd3ebd2c,0x3d46bd22,0x3d043d5c,0xbd6d3cc4,0xbc79bd78,0x3d7fbbc9,0xbb493d80,0xbd7bbc48,0x3cacbd71,0x3d623cf1,0xbd183d4e,
0xbd35bd35,0x3d4ebd18,0x3cf13d62,0xbd713cac,0xbc48bd7b,0x3d80bb49,0xbbc93d7f,0xbd78bc79,0x3cc4bd6d,0x3d5c3d04,0xbd223d46,0xbd2cbd3e,0x3d55bd0e,0x3cdb3d67,0xbd753c95,0xbc16bd7d,
0xbd7b3c48,0x3c16bd7d,0x3d623cf1,0xbd3e3d2c,0x3d80,0xbd71bcac,0x3d22bd46,0x3d043d5c,0x3d55bd0e,0x3c793d78,0xbd7fbbc9,0x3cdbbd67,0xbcc4bd6d,0x3d80bb49,0xbc953d75,0xbd4ebd18,
0xbd0e3d55,0xbd18bd4e,0x3d75bc95,0xbb493d80,0x3d353d35,0xbd673cdb,0xbbc9bd7f,0x3d783c79,0x3c48bd7b,0x3d5c3d04,0xbd463d22,0xbcacbd71,0xbd6dbcc4,0x3d2cbd3e,0x3cf13d62,0xbd7d3c16,
0x3d6dbcc4,0xbc163d7d,0xbd46bd22,0x3d71bcac,0xbc483d7b,0xbd3ebd2c,0x3d75bc95,0xbc793d78,0x3d80,0xbd5cbd04,0x3d62bcf1,0xbb493d80,0xbd55bd0e,0x3d67bcdb,0xbbc93d7f,0xbd4ebd18,
0xbcc43d6d,0xbd18bd4e,0x3d7fbbc9,0xbcdb3d67,0xbd0ebd55,0x3d80bb49,0xbcf13d62,0xbd04bd5c,0xbd35bd35,0x3d78bc79,0xbc953d75,0xbd2cbd3e,0x3d7bbc48,0xbcac3d71,0xbd22bd46,0x3d7dbc16,
0xbd0ebd55,0x3d7d3c16,0xbd463d22,0x3b49bd80,0x3cc43d6d,0xbd71bcac,0x3d62bcf1,0xbc793d78,0xbc48bd7b,0x3d5c3d04,0xbd753c95,0x3cdbbd67,0x3d80,0xbd3ebd2c,0x3d7fbbc9,0xbd183d4e,
0xbd7bbc48,0x3d4ebd18,0xbbc93d7f,0xbd2cbd3e,0x3d6d3cc4,0xbd673cdb,0x3c95bd75,0x3d043d5c,0xbd55bd0e,0x3d78bc79,0xbcf13d62,0xbcacbd71,0x3d353d35,0xbd803b49,0x3d22bd46,0x3c163d7d,
0xbd35bd35,0x3d7d3c16,0xbd623cf1,0x3cdbbd67,0x3c483d7b,0xbd3ebd2c,0x3d7f3bc9,0xbd5c3d04,0x3cc4bd6d,0x3c793d78,0xbd46bd22,0x3d803b49,0xbd553d0e,0x3cacbd71,0x3c953d75,0xbd4ebd18,
0x3d80,0xbd18bd4e,0x3d753c95,0xbd713cac,0x3d0ebd55,0x3b493d80,0xbd22bd46,0x3d783c79,0xbd6d3cc4,0x3d04bd5c,0x3bc93d7f,0xbd2cbd3e,0x3d7b3c48,0xbd673cdb,0x3cf1bd62,0x3c163d7d,
0x3d0ebd55,0xbc163d7d,0xbc95bd75,0x3d2c3d3e,0x3d353d35,0xbd71bcac,0x3d7fbbc9,0xbd5c3d04,0xbc483d7b,0xbc79bd78,0x3d223d46,0xbd67bcdb,0xbd6dbcc4,0x3d80bb49,0xbd623cf1,0x3d18bd4e,
0x3d7bbc48,0xbd4e3d18,0x3cf1bd62,0xbb493d80,0x3d80,0xbcdbbd67,0x3d463d22,0xbd78bc79,0xbd553d0e,0x3d04bd5c,0xbbc93d7f,0xbcacbd71,0xbcc4bd6d,0x3d3e3d2c,0xbd75bc95,0x3d7dbc16,
0xbcc43d6d,0x3c16bd7d,0x3bc93d7f,0xbcacbd71,0x3d0e3d55,0xbd3ebd2c,0x3d623cf1,0xbd78bc79,0xbd35bd35,0x3d5c3d04,0xbd75bc95,0x3d803b49,0xbd7b3c48,0x3d67bcdb,0xbd463d22,0x3d18bd4e,
0x3d6dbcc4,0xbd4e3d18,0x3d22bd46,0xbcdb3d67,0x3c48bd7b,0x3b493d80,0xbc95bd75,0x3d043d5c,0x3d80,0xbc79bd78,0x3cf13d62,0xbd2cbd3e,0x3d553d0e,0xbd71bcac,0x3d7f3bc9,0xbd7d3c16,
0x3d7b3c48,0xbd7dbc16,0x3d7f3bc9,0xbd80bb49,0x3d6d3cc4,0xbd71bcac,0x3d753c95,0xbd78bc79,0x3d553d0e,0xbd5cbd04,0x3d623cf1,0xbd67bcdb,0x3d353d35,0xbd3ebd2c,0x3d463d22,0xbd4ebd18,
0x3d0e3d55,0xbd18bd4e,0x3d223d46,0xbd2cbd3e,0x3cc43d6d,0xbcdbbd67,0x3cf13d62,0xbd04bd5c,0x3c483d7b,0xbc79bd78,0x3c953d75,0xbcacbd71,0x3d80,0xbb49bd80,0x3bc93d7f,0xbc16bd7d,
0xbd800000,0x3c16bd7d,0x3d753c95,0xbcdb3d67,0xbd55bd0e,0x3d2cbd3e,0x3d223d46,0xbd5c3d04,0xbcc4bd6d,0x3d78bc79,0x3bc93d7f,0xbd80bb49,0x3c48bd7b,0x3d713cac,0xbcf13d62,0xbd4ebd18,
0x3d35bd35,0x3d183d4e,0xbd623cf1,0xbcacbd71,0x3d7bbc48,0x3b493d80,0xbd7fbbc9,0x3c79bd78,0x3d6d3cc4,0xbd043d5c,0xbd46bd22,0x3d3ebd2c,0x3d0e3d55,0xbd673cdb,0xbc95bd75,0x3d7dbc16,
0xbc48bd7b,0x3d7d3c16,0xbcf13d62,0xbd2cbd3e,0xbd800000,0x3cacbd71,0x3d463d22,0xbd5c3d04,0x3d0e3d55,0xbd783c79,0x3bc9bd7f,0x3d673cdb,0x3d6dbcc4,0x3b493d80,0xbd75bc95,0x3d18bd4e,
0xbd55bd0e,0x3d4ebd18,0x3c953d75,0xbd80bb49,0xbd353d35,0xbcdbbd67,0x3d7fbbc9,0xbc793d78,0x3d7b3c48,0xbd043d5c,0xbd22bd46,0x3d71bcac,0x3cc4bd6d,0x3d3e3d2c,0xbd623cf1,0xbc16bd7d,
0x3cc43d6d,0xbd7dbc16,0x3d22bd46,0x3cac3d71,0xbd7bbc48,0x3d2cbd3e,0x3c953d75,0xbd78bc79,0xbd800000,0x3d04bd5c,0x3cf13d62,0xbd80bb49,0x3d0ebd55,0x3cdb3d67,0xbd7fbbc9,0x3d18bd4e,
0xbd6dbcc4,0x3d4ebd18,0x3bc93d7f,0xbd67bcdb,0x3d55bd0e,0x3b493d80,0xbd62bcf1,0x3d5cbd04,0x3d35bd35,0x3c793d78,0xbd75bc95,0x3d3ebd2c,0x3c483d7b,0xbd71bcac,0x3d46bd22,0x3c163d7d,
0x3d55bd0e,0xbc163d7d,0xbd22bd46,0x3d803b49,0xbd6d3cc4,0x3cacbd71,0x3cf13d62,0xbd78bc79,0x3d7bbc48,0xbd043d5c,0xbc95bd75,0x3d673cdb,0xbd800000,0x3d2cbd3e,0x3bc93d7f,0xbd4ebd18,
0x3c48bd7b,0x3d183d4e,0xbd7fbbc9,0x3d3ebd2c,0xbcc43d6d,0xbcdbbd67,0x3d753c95,0xbd5c3d04,0x3d0ebd55,0x3c793d78,0xbd62bcf1,0x3d71bcac,0xbd353d35,0xbb49bd80,0x3d463d22,0xbd7d3c16,
0x3d35bd35,0xbc163d7d,0xbcf1bd62,0x3d673cdb,0xbd7b3c48,0x3d2cbd3e,0xbbc93d7f,0xbd04bd5c,0x3d6d3cc4,0xbd783c79,0x3d22bd46,0xbb493d80,0xbd0ebd55,0x3d713cac,0xbd753c95,0x3d18bd4e,
0xbd800000,0x3d4ebd18,0xbc953d75,0xbcacbd71,0x3d553d0e,0xbd803b49,0x3d46bd22,0xbc793d78,0xbcc4bd6d,0x3d5c3d04,0xbd7f3bc9,0x3d3ebd2c,0xbc483d7b,0xbcdbbd67,0x3d623cf1,0xbd7d3c16,
0x3d553d0e,0xbd7dbc16,0x3d75bc95,0xbd3e3d2c,0xbd353d35,0x3cacbd71,0x3bc93d7f,0xbd04bd5c,0xbd7bbc48,0x3d78bc79,0xbd463d22,0x3cdbbd67,0x3cc4bd6d,0x3b493d80,0xbcf1bd62,0x3d4e3d18,
0x3c483d7b,0xbd18bd4e,0x3d623cf1,0xbd80bb49,0xbd800000,0x3d67bcdb,0xbd223d46,0x3c79bd78,0xbd0ebd55,0x3d5c3d04,0xbd7fbbc9,0x3d71bcac,0x3d6dbcc4,0xbd2c3d3e,0x3c95bd75,0x3c163d7d,
0xbd6dbcc4,0x3d7d3c16,0xbd7f3bc9,0x3d71bcac,0xbd553d0e,0x3d2cbd3e,0xbcf13d62,0x3c79bd78,0x3d35bd35,0xbd043d5c,0x3c95bd75,0xbb493d80,0xbc48bd7b,0x3cdb3d67,0xbd22bd46,0x3d4e3d18,
0x3cc43d6d,0xbd18bd4e,0x3d463d22,0xbd67bcdb,0x3d7b3c48,0xbd803b49,0x3d75bc95,0xbd5c3d04,0xbd800000,0x3d78bc79,0xbd623cf1,0x3d3ebd2c,0xbd0e3d55,0x3cacbd71,0xbbc93d7f,0xbc16bd7d,
0xbc483d7b,0x3c16bd7d,0xbbc93d7f,0x3b49bd80,0xbcc43d6d,0x3cacbd71,0xbc953d75,0x3c79bd78,0xbd0e3d55,0x3d04bd5c,0xbcf13d62,0x3cdbbd67,0xbd353d35,0x3d2cbd3e,0xbd223d46,0x3d18bd4e,
0xbd553d0e,0x3d4ebd18,0xbd463d22,0x3d3ebd2c,0xbd6d3cc4,0x3d67bcdb,0xbd623cf1,0x3d5cbd04,0xbd7b3c48,0x3d78bc79,0xbd753c95,0x3d71bcac,0xbd800000,0x3d80bb49,0xbd7f3bc9,0x3d7dbc16,
0x3d80,0x3c16bd7d,0xbc953d75,0x3cdbbd67,0xbd0e3d55,0x3d2cbd3e,0xbd463d22,0x3d5cbd04,0xbd6d3cc4,0x3d78bc79,0xbd7f3bc9,0x3d803b49,0xbd7bbc48,0x3d713cac,0xbd62bcf1,0x3d4e3d18,
0xbd35bd35,0x3d183d4e,0xbcf1bd62,0x3cac3d71,0xbc48bd7b,0x3b493d80,0x3bc9bd7f,0xbc793d78,0x3cc4bd6d,0xbd043d5c,0x3d22bd46,0xbd3e3d2c,0x3d55bd0e,0xbd673cdb,0x3d75bc95,0xbd7d3c16,
0xbd7b3c48,0x3d7d3c16,0xbd62bcf1,0x3d2c3d3e,0x3d80,0x3cacbd71,0xbd223d46,0x3d5cbd04,0x3d55bd0e,0xbd783c79,0x3d7f3bc9,0xbd67bcdb,0xbcc4bd6d,0x3b493d80,0x3c95bd75,0xbd183d4e,
0xbd0e3d55,0x3d4ebd18,0xbd753c95,0x3d803b49,0x3d353d35,0xbcdbbd67,0x3bc93d7f,0x3c79bd78,0x3c48bd7b,0xbd043d5c,0x3d46bd22,0xbd713cac,0xbd6dbcc4,0x3d3e3d2c,0xbcf1bd62,0x3c163d7d,
0x3d6dbcc4,0xbd7dbc16,0x3d463d22,0xbcacbd71,0xbc483d7b,0x3d2cbd3e,0xbd753c95,0x3d783c79,0x3d80,0x3d04bd5c,0xbd623cf1,0x3d803b49,0xbd55bd0e,0x3cdb3d67,0x3bc9bd7f,0xbd183d4e,
0xbcc43d6d,0x3d4ebd18,0xbd7f3bc9,0x3d673cdb,0xbd0ebd55,0x3b493d80,0x3cf1bd62,0xbd5c3d04,0xbd35bd35,0x3c793d78,0x3c95bd75,0xbd3e3d2c,0x3d7bbc48,0xbd71bcac,0x3d223d46,0xbc16bd7d,
0xbd0ebd55,0xbc163d7d,0x3d46bd22,0xbd80bb49,0x3cc43d6d,0x3cacbd71,0xbd623cf1,0x3d783c79,0xbc48bd7b,0xbd043d5c,0x3d75bc95,0xbd67bcdb,0x3d80,0x3d2cbd3e,0xbd7f3bc9,0x3d4e3d18,
0xbd7bbc48,0x3d183d4e,0x3bc9bd7f,0xbd3e3d2c,0x3d6d3cc4,0xbcdbbd67,0xbc953d75,0x3d5cbd04,0xbd55bd0e,0x3c793d78,0x3cf1bd62,0xbd713cac,0x3d353d35,0xbb49bd80,0xbd223d46,0x3d7dbc16,
0xbd35bd35,0xbc163d7d,0x3d62bcf1,0xbd67bcdb,0x3c483d7b,0x3d2cbd3e,0xbd7fbbc9,0x3d043d5c,0x3cc4bd6d,0xbd783c79,0x3d463d22,0x3b49bd80,0xbd553d0e,0x3d713cac,0xbc95bd75,0xbd183d4e,
0x3d80,0x3d4ebd18,0xbd75bc95,0x3cac3d71,0x3d0ebd55,0xbd803b49,0x3d223d46,0x3c79bd78,0xbd6d3cc4,0x3d5c3d04,0xbbc9bd7f,0xbd3e3d2c,0x3d7b3c48,0xbcdbbd67,0xbcf13d62,0x3d7dbc16,
0x3d0ebd55,0xbd7dbc16,0x3c953d75,0x3d3ebd2c,0x3d353d35,0x3cacbd71,0xbd7f3bc9,0x3d043d5c,0xbc483d7b,0x3d78bc79,0xbd22bd46,0xbcdb3d67,0xbd6dbcc4,0x3b493d80,0x3d62bcf1,0xbd4ebd18,
0x3d7bbc48,0xbd18bd4e,0xbcf13d62,0x3d803b49,0x3d80,0x3d67bcdb,0xbd46bd22,0xbc793d78,0xbd553d0e,0x3d5c3d04,0x3bc9bd7f,0xbd713cac,0xbcc4bd6d,0xbd2c3d3e,0x3d753c95,0xbc16bd7d,
0xbcc43d6d,0x3d7d3c16,0xbbc9bd7f,0xbd713cac,0x3d0e3d55,0x3d2cbd3e,0xbd62bcf1,0xbc793d78,0xbd35bd35,0xbd043d5c,0x3d753c95,0x3b49bd80,0xbd7b3c48,0x3cdb3d67,0x3d46bd22,0xbd4ebd18,
0x3d6dbcc4,0xbd18bd4e,0xbd223d46,0x3d673cdb,0x3c48bd7b,0xbd803b49,0x3c953d75,0x3d5cbd04,0x3d80,0x3d78bc79,0xbcf1bd62,0xbd3e3d2c,0x3d553d0e,0x3cacbd71,0xbd7fbbc9,0x3c163d7d,
0x3d7b3c48,0x3c16bd7d,0xbd7fbbc9,0xbb493d80,0x3d6d3cc4,0x3cacbd71,0xbd75bc95,0xbc793d78,0x3d553d0e,0x3d04bd5c,0xbd62bcf1,0xbcdb3d67,0x3d353d35,0x3d2cbd3e,0xbd46bd22,0xbd183d4e,
0x3d0e3d55,0x3d4ebd18,0xbd22bd46,0xbd3e3d2c,0x3cc43d6d,0x3d67bcdb,0xbcf1bd62,0xbd5c3d04,0x3c483d7b,0x3d78bc79,0xbc95bd75,0xbd713cac,0x3d80,0x3d80bb49,0xbbc9bd7f,0xbd7d3c16,
0xbd800000,0x3d7d3c16,0xbd75bc95,0x3d673cdb,0xbd55bd0e,0x3d3e3d2c,0xbd22bd46,0x3d043d5c,0xbcc4bd6d,0x3c793d78,0xbbc9bd7f,0xbb493d80,0x3c48bd7b,0xbcac3d71,0x3cf1bd62,0xbd183d4e,
0x3d35bd35,0xbd4e3d18,0x3d62bcf1,0xbd713cac,0x3d7bbc48,0xbd803b49,0x3d7f3bc9,0xbd78bc79,0x3d6d3cc4,0xbd5cbd04,0x3d463d22,0xbd2cbd3e,0x3d0e3d55,0xbcdbbd67,0x3c953d75,0xbc16bd7d,
0xbc48bd7b,0xbc163d7d,0x3cf1bd62,0xbd3e3d2c,0xbd800000,0x3d713cac,0xbd46bd22,0x3d043d5c,0x3d0e3d55,0xbc79bd78,0xbbc93d7f,0x3cdbbd67,0x3d6dbcc4,0xbd803b49,0x3d753c95,0xbd4ebd18,
0xbd55bd0e,0x3d183d4e,0xbc95bd75,0xbb493d80,0xbd353d35,0x3d67bcdb,0xbd7f3bc9,0x3d783c79,0x3d7b3c48,0xbd5cbd04,0x3d223d46,0xbcacbd71,0x3cc4bd6d,0xbd2c3d3e,0x3d62bcf1,0xbd7d3c16,
0x3cc43d6d,0x3c16bd7d,0xbd223d46,0x3d71bcac,0xbd7bbc48,0x3d3e3d2c,0xbc95bd75,0xbc793d78,0xbd800000,0x3d5c3d04,0xbcf1bd62,0xbb493d80,0x3d0ebd55,0xbd673cdb,0x3d7f3bc9,0xbd4ebd18,
0xbd6dbcc4,0x3d183d4e,0xbbc9bd7f,0xbcdb3d67,0x3d55bd0e,0xbd803b49,0x3d623cf1,0xbd04bd5c,0x3d35bd35,0xbd783c79,0x3d753c95,0xbd2cbd3e,0x3c483d7b,0x3cacbd71,0xbd463d22,0x3d7dbc16,
0x3d55bd0e,0xbd7dbc16,0x3d223d46,0x3b49bd80,0xbd6d3cc4,0x3d713cac,0xbcf1bd62,0xbc793d78,0x3d7bbc48,0xbd5cbd04,0x3c953d75,0x3cdbbd67,0xbd800000,0x3d3e3d2c,0xbbc9bd7f,0xbd183d4e,
0x3c48bd7b,0xbd4e3d18,0x3d7f3bc9,0xbd2cbd3e,0xbcc43d6d,0x3d67bcdb,0xbd75bc95,0x3d043d5c,0x3d0ebd55,0xbd783c79,0x3d623cf1,0xbcacbd71,0xbd353d35,0x3d80bb49,0xbd46bd22,0x3c163d7d,
0x3d35bd35,0xbd7dbc16,0x3cf13d62,0x3cdbbd67,0xbd7b3c48,0x3d3e3d2c,0x3bc9bd7f,0xbd5c3d04,0x3d6d3cc4,0xbc79bd78,0xbd223d46,0x3d803b49,0xbd0ebd55,0xbcac3d71,0x3d75bc95,0xbd4ebd18,
0xbd800000,0x3d183d4e,0x3c95bd75,0xbd713cac,0x3d553d0e,0xbb49bd80,0xbd463d22,0x3d783c79,0xbcc4bd6d,0xbd043d5c,0x3d7fbbc9,0xbd2cbd3e,0xbc483d7b,0x3d67bcdb,0xbd62bcf1,0x3c163d7d,
0x3d553d0e,0x3c16bd7d,0xbd753c95,0x3d2c3d3e,0xbd353d35,0x3d713cac,0xbbc9bd7f,0xbd5c3d04,0xbd7bbc48,0x3c793d78,0x3d46bd22,0xbd67bcdb,0x3cc4bd6d,0xbd803b49,0x3cf13d62,0x3d18bd4e,
0x3c483d7b,0x3d4ebd18,0xbd62bcf1,0xbb493d80,0xbd800000,0x3cdb3d67,0x3d22bd46,0xbd78bc79,0xbd0ebd55,0xbd043d5c,0x3d7f3bc9,0xbcacbd71,0x3d6dbcc4,0xbd3ebd2c,0xbc953d75,0x3d7dbc16,
0xbd6dbcc4,0xbc163d7d,0x3d7fbbc9,0xbcacbd71,0xbd553d0e,0x3d3e3d2c,0x3cf1bd62,0xbd78bc79,0x3d35bd35,0xbd5cbd04,0xbc953d75,0x3d803b49,0xbc48bd7b,0xbd673cdb,0x3d223d46,0x3d18bd4e,
0x3cc43d6d,0x3d4ebd18,0xbd46bd22,0xbcdb3d67,0x3d7b3c48,0xbb49bd80,0xbd753c95,0x3d043d5c,0xbd800000,0x3c793d78,0x3d62bcf1,0xbd2cbd3e,0xbd0e3d55,0x3d713cac,0x3bc9bd7f,0xbd7d3c16,
0xbc483d7b,0x3d7d3c16,0x3bc9bd7f,0xbd80bb49,0xbcc43d6d,0x3d713cac,0x3c95bd75,0xbd78bc79,0xbd0e3d55,0x3d5c3d04,0x3cf1bd62,0xbd67bcdb,0xbd353d35,0x3d3e3d2c,0x3d22bd46,0xbd4ebd18,
0xbd553d0e,0x3d183d4e,0x3d46bd22,0xbd2cbd3e,0xbd6d3cc4,0x3cdb3d67,0x3d62bcf1,0xbd04bd5c,0xbd7b3c48,0x3c793d78,0x3d75bc95,0xbcacbd71,0xbd800000,0x3b493d80,0x3d7fbbc9,0xbc16bd7d,
0x3d80,0x3d7d3c16,0x3c95bd75,0xbd67bcdb,0xbd0e3d55,0x3d3e3d2c,0x3d46bd22,0xbd04bd5c,0xbd6d3cc4,0x3c793d78,0x3d7fbbc9,0x3b49bd80,0xbd7bbc48,0xbcac3d71,0x3d623cf1,0x3d18bd4e,
0xbd35bd35,0xbd4e3d18,0x3cf13d62,0x3d71bcac,0xbc48bd7b,0xbd803b49,0xbbc93d7f,0x3d783c79,0x3cc4bd6d,0xbd5cbd04,0xbd223d46,0x3d2c3d3e,0x3d55bd0e,0xbcdbbd67,0xbd753c95,0x3c163d7d,
0xbd7b3c48,0xbc163d7d,0x3d623cf1,0x3d3ebd2c,0x3d80,0x3d713cac,0x3d22bd46,0xbd04bd5c,0x3d55bd0e,0xbc79bd78,0xbd7fbbc9,0xbcdb3d67,0xbcc4bd6d,0xbd803b49,0xbc953d75,0x3d4e3d18,
0xbd0e3d55,0x3d183d4e,0x3d75bc95,0x3b49bd80,0x3d353d35,0x3d67bcdb,0xbbc9bd7f,0xbd78bc79,0x3c48bd7b,0xbd5cbd04,0xbd463d22,0x3cac3d71,0xbd6dbcc4,0xbd2c3d3e,0x3cf13d62,0x3d7dbc16,
0x3d6dbcc4,0x3c16bd7d,0xbd46bd22,0xbd713cac,0xbc483d7b,0x3d3e3d2c,0x3d75bc95,0x3c79bd78,0x3d80,0x3d5c3d04,0x3d62bcf1,0x3b49bd80,0xbd55bd0e,0xbd673cdb,0xbbc93d7f,0x3d4e3d18,
0xbcc43d6d,0x3d183d4e,0x3d7fbbc9,0x3cdbbd67,0xbd0ebd55,0xbd803b49,0xbcf13d62,0x3d043d5c,0xbd35bd35,0xbd783c79,0xbc953d75,0x3d2c3d3e,0x3d7bbc48,0x3cacbd71,0xbd22bd46,0xbd7d3c16,
0xbd0ebd55,0xbd7dbc16,0xbd463d22,0xbb493d80,0x3cc43d6d,0x3d713cac,0x3d62bcf1,0x3c79bd78,0xbc48bd7b,0xbd5cbd04,0xbd753c95,0xbcdb3d67,0x3d80,0x3d3e3d2c,0x3d7fbbc9,0x3d18bd4e,
0xbd7bbc48,0xbd4e3d18,0xbbc93d7f,0x3d2c3d3e,0x3d6d3cc4,0x3d67bcdb,0x3c95bd75,0xbd04bd5c,0xbd55bd0e,0xbd783c79,0xbcf13d62,0x3cac3d71,0x3d353d35,0x3d80bb49,0x3d22bd46,0xbc16bd7d,
0xbd35bd35,0xbd7dbc16,0xbd623cf1,0xbcdb3d67,0x3c483d7b,0x3d3e3d2c,0x3d7f3bc9,0x3d5cbd04,0x3cc4bd6d,0xbc79bd78,0xbd46bd22,0xbd80bb49,0xbd553d0e,0xbcac3d71,0x3c953d75,0x3d4e3d18,
0x3d80,0x3d183d4e,0x3d753c95,0x3d71bcac,0x3d0ebd55,0xbb49bd80,0xbd22bd46,0xbd78bc79,0xbd6d3cc4,0xbd043d5c,0x3bc93d7f,0x3d2c3d3e,0x3d7b3c48,0x3d67bcdb,0x3cf1bd62,0xbc16bd7d,
0x3d0ebd55,0x3c16bd7d,0xbc95bd75,0xbd2cbd3e,0x3d353d35,0x3d713cac,0x3d7fbbc9,0x3d5cbd04,0xbc483d7b,0x3c793d78,0x3d223d46,0x3d673cdb,0xbd6dbcc4,0xbd803b49,0xbd623cf1,0xbd183d4e,
0x3d7bbc48,0x3d4ebd18,0x3cf1bd62,0x3b49bd80,0x3d80,0x3cdb3d67,0x3d463d22,0x3d783c79,0xbd553d0e,0xbd043d5c,0xbbc93d7f,0x3cac3d71,0xbcc4bd6d,0xbd3ebd2c,0xbd75bc95,0xbd7d3c16,
0xbcc43d6d,0xbc163d7d,0x3bc93d7f,0x3cac3d71,0x3d0e3d55,0x3d3e3d2c,0x3d623cf1,0x3d783c79,0xbd35bd35,0xbd5cbd04,0xbd75bc95,0xbd80bb49,0xbd7b3c48,0xbd673cdb,0xbd463d22,0xbd183d4e,
0x3d6dbcc4,0x3d4ebd18,0x3d22bd46,0x3cdbbd67,0x3c48bd7b,0xbb49bd80,0xbc95bd75,0xbd04bd5c,0x3d80,0x3c793d78,0x3cf13d62,0x3d2c3d3e,0x3d553d0e,0x3d713cac,0x3d7f3bc9,0x3d7dbc16,
0x3d7b3c48,0x3d7d3c16,0x3d7f3bc9,0x3d803b49,0x3d6d3cc4,0x3d713cac,0x3d753c95,0x3d783c79,0x3d553d0e,0x3d5c3d04,0x3d623cf1,0x3d673cdb,0x3d353d35,0x3d3e3d2c,0x3d463d22,0x3d4e3d18,
0x3d0e3d55,0x3d183d4e,0x3d223d46,0x3d2c3d3e,0x3cc43d6d,0x3cdb3d67,0x3cf13d62,0x3d043d5c,0x3c483d7b,0x3c793d78,0x3c953d75,0x3cac3d71,0x3d80,0x3b493d80,0x3bc93d7f,0x3c163d7d,
0xbd800000,0xbc163d7d,0x3d753c95,0x3cdbbd67,0xbd55bd0e,0xbd2c3d3e,0x3d223d46,0x3d5cbd04,0xbcc4bd6d,0xbd783c79,0x3bc93d7f,0x3d803b49,0x3c48bd7b,0xbd71bcac,0xbcf13d62,0x3d4e3d18,
0x3d35bd35,0xbd18bd4e,0xbd623cf1,0x3cac3d71,0x3d7bbc48,0xbb49bd80,0xbd7fbbc9,0xbc793d78,0x3d6d3cc4,0x3d04bd5c,0xbd46bd22,0xbd3e3d2c,0x3d0e3d55,0x3d67bcdb,0xbc95bd75,0xbd7d3c16,
0xbc48bd7b,0xbd7dbc16,0xbcf13d62,0x3d2c3d3e,0xbd800000,0xbcac3d71,0x3d463d22,0x3d5cbd04,0x3d0e3d55,0x3d78bc79,0x3bc9bd7f,0xbd67bcdb,0x3d6dbcc4,0xbb49bd80,0xbd75bc95,0xbd183d4e,
0xbd55bd0e,0xbd4e3d18,0x3c953d75,0x3d803b49,0xbd353d35,0x3cdb3d67,0x3d7fbbc9,0x3c79bd78,0x3d7b3c48,0x3d04bd5c,0xbd22bd46,0xbd713cac,0x3cc4bd6d,0xbd3ebd2c,0xbd623cf1,0x3c163d7d,
0x3cc43d6d,0x3d7d3c16,0x3d22bd46,0xbcacbd71,0xbd7bbc48,0xbd2c3d3e,0x3c953d75,0x3d783c79,0xbd800000,0xbd043d5c,0x3cf13d62,0x3d803b49,0x3d0ebd55,0xbcdbbd67,0xbd7fbbc9,0xbd183d4e,
0xbd6dbcc4,0xbd4e3d18,0x3bc93d7f,0x3d673cdb,0x3d55bd0e,0xbb49bd80,0xbd62bcf1,0xbd5c3d04,0x3d35bd35,0xbc79bd78,0xbd75bc95,0xbd3e3d2c,0x3c483d7b,0x3d713cac,0x3d46bd22,0xbc16bd7d,
0x3d55bd0e,0x3c16bd7d,0xbd22bd46,0xbd80bb49,0xbd6d3cc4,0xbcac3d71,0x3cf13d62,0x3d783c79,0x3d7bbc48,0x3d04bd5c,0xbc95bd75,0xbd67bcdb,0xbd800000,0xbd2c3d3e,0x3bc93d7f,0x3d4e3d18,
0x3c48bd7b,0xbd18bd4e,0xbd7fbbc9,0xbd3e3d2c,0xbcc43d6d,0x3cdb3d67,0x3d753c95,0x3d5cbd04,0x3d0ebd55,0xbc79bd78,0xbd62bcf1,0xbd713cac,0xbd353d35,0x3b493d80,0x3d463d22,0x3d7dbc16,
0x3d35bd35,0x3c16bd7d,0xbcf1bd62,0xbd67bcdb,0xbd7b3c48,0xbd2c3d3e,0xbbc93d7f,0x3d043d5c,0x3d6d3cc4,0x3d78bc79,0x3d22bd46,0x3b49bd80,0xbd0ebd55,0xbd71bcac,0xbd753c95,0xbd183d4e,
0xbd800000,0xbd4e3d18,0xbc953d75,0x3cac3d71,0x3d553d0e,0x3d80bb49,0x3d46bd22,0x3c79bd78,0xbcc4bd6d,0xbd5cbd04,0xbd7f3bc9,0xbd3e3d2c,0xbc483d7b,0x3cdb3d67,0x3d623cf1,0x3d7dbc16,
0x3d553d0e,0x3d7d3c16,0x3d75bc95,0x3d3ebd2c,0xbd353d35,0xbcac3d71,0x3bc93d7f,0x3d043d5c,0xbd7bbc48,0xbd783c79,0xbd463d22,0xbcdb3d67,0x3cc4bd6d,0xbb49bd80,0xbcf1bd62,0xbd4ebd18,
0x3c483d7b,0x3d183d4e,0x3d623cf1,0x3d803b49,0xbd800000,0xbd673cdb,0xbd223d46,0xbc793d78,0xbd0ebd55,0xbd5cbd04,0xbd7fbbc9,0xbd713cac,0x3d6dbcc4,0x3d2cbd3e,0x3c95bd75,0xbc16bd7d,
0xbd6dbcc4,0xbd7dbc16,0xbd7f3bc9,0xbd713cac,0xbd553d0e,0xbd2c3d3e,0xbcf13d62,0xbc793d78,0x3d35bd35,0x3d04bd5c,0x3c95bd75,0x3b49bd80,0xbc48bd7b,0xbcdbbd67,0xbd22bd46,0xbd4ebd18,
0x3cc43d6d,0x3d183d4e,0x3d463d22,0x3d673cdb,0x3d7b3c48,0x3d80bb49,0x3d75bc95,0x3d5cbd04,0xbd800000,0xbd783c79,0xbd623cf1,0xbd3e3d2c,0xbd0e3d55,0xbcac3d71,0xbbc93d7f,0x3c163d7d,
0xbc483d7b,0xbc163d7d,0xbbc93d7f,0xbb493d80,0xbcc43d6d,0xbcac3d71,0xbc953d75,0xbc793d78,0xbd0e3d55,0xbd043d5c,0xbcf13d62,0xbcdb3d67,0xbd353d35,0xbd2c3d3e,0xbd223d46,0xbd183d4e,
0xbd553d0e,0xbd4e3d18,0xbd463d22,0xbd3e3d2c,0xbd6d3cc4,0xbd673cdb,0xbd623cf1,0xbd5c3d04,0xbd7b3c48,0xbd783c79,0xbd753c95,0xbd713cac,0xbd800000,0xbd803b49,0xbd7f3bc9,0xbd7d3c16,
0x3f003f00,0xbf003f00,0x3f003f00,0xbf003f00,0x3f003f00,0xbf003f00,0x3f003f00,0xbf003f00,0x3f003f00,0xbf003f00,0x3f003f00,0xbf003f00,0x3f003f00,0xbf003f00,0x3f003f00,0xbf003f00,
0x3eff3f00,0xbd490000,0x3ea23eb5,0xbec6beb5,0x3ef53efb,0xbe15bdc8,0x3e713e8e,0xbee2bed5,0x3ee23eed,0xbe71be44,0x3e153e44,0xbef5beed,0x3ec63ed5,0xbea2be8e,0x3d493dc8,0xbeffbefb,
0x3efb3f00,0xbdc80000,0xbdc80000,0xbefbbf00,0x3ed53eed,0xbe8ebe44,0xbe8ebe44,0xbed5beed,0x3e8e3eb5,0xbed5beb5,0xbed5beb5,0xbe8ebeb5,0x3dc83e44,0xbefbbeed,0xbefbbeed,0xbdc8be44,
0x3ef53f00,0xbe150000,0xbee2beb5,0xbe71beb5,0x3ea23ed5,0xbec6be8e,0xbeffbefb,0x3d49bdc8,0x3d493e44,0xbeffbeed,0xbec6beed,0x3ea23e44,0xbe71bdc8,0xbee2befb,0xbe15be8e,0x3ef53ed5,
0x3eed3f00,0xbe440000,0xbeedbf00,0x3e440000,0x3e443eb5,0xbeedbeb5,0xbe44beb5,0x3eed3eb5,0xbe440000,0xbeedbf00,0x3e440000,0x3eed3f00,0xbeedbeb5,0xbe44beb5,0x3eed3eb5,0x3e443eb5,
0x3ee23f00,0xbe710000,0xbe15beb5,0x3ef53eb5,0x3d493e8e,0xbeffbed5,0x3ea23dc8,0x3ec63efb,0xbec6be44,0xbea2beed,0x3eff3eed,0xbd493e44,0xbef5befb,0x3e15bdc8,0x3e713ed5,0xbee2be8e,
0x3ed53f00,0xbe8e0000,0x3e8e0000,0x3ed53f00,0xbdc83e44,0xbefbbeed,0x3efb3eed,0xbdc83e44,0xbefbbeb5,0xbdc8beb5,0x3dc83eb5,0xbefbbeb5,0xbe8ebeed,0x3ed53e44,0xbed5be44,0xbe8ebeed,
0x3ec63f00,0xbea20000,0x3eff3eb5,0x3d493eb5,0xbe713dc8,0xbee2befb,0x3e153ed5,0xbef5be8e,0xbef5beed,0x3e15be44,0xbee2be44,0xbe71beed,0x3d49be8e,0x3eff3ed5,0xbea2befb,0x3ec63dc8,
0x3f00,0xbf000000,0x3f00,0xbf000000,0xbf00,0x3f000000,0xbf00,0x3f000000,0x3f00,0xbf000000,0x3f00,0xbf000000,0xbf00,0x3f000000,0xbf00,0x3f000000,
0xbd493f00,0xbeff0000,0xbec63eb5,0xbea2beb5,0x3e15befb,0x3ef53dc8,0x3ee2be8e,0x3e713ed5,0xbe713eed,0xbee2be44,0xbef53e44,0xbe15beed,0x3ea2bed5,0x3ec63e8e,0x3effbdc8,0x3d493efb,
0xbdc83f00,0xbefb0000,0xbefb0000,0x3dc8bf00,0x3e8ebeed,0x3ed53e44,0x3ed53e44,0xbe8e3eed,0xbed53eb5,0xbe8ebeb5,0xbe8ebeb5,0x3ed5beb5,0x3efbbe44,0x3dc83eed,0x3dc83eed,0xbefb3e44,
0xbe153f00,0xbef50000,0xbe71beb5,0x3ee2beb5,0x3ec6bed5,0x3ea23e8e,0xbd493efb,0xbeff3dc8,0xbeff3e44,0xbd49beed,0x3ea2beed,0x3ec63e44,0x3ee23dc8,0xbe713efb,0xbef53e8e,0xbe15bed5,
0xbe443f00,0xbeed0000,0x3e44bf00,0x3eed0000,0x3eedbeb5,0x3e443eb5,0xbeed3eb5,0xbe44beb5,0xbeed0000,0x3e44bf00,0x3eed0000,0xbe443f00,0x3e443eb5,0xbeed3eb5,0xbe44beb5,0x3eedbeb5,
0xbe713f00,0xbee20000,0x3ef5beb5,0x3e153eb5,0x3effbe8e,0x3d493ed5,0xbec6bdc8,0x3ea2befb,0xbea2be44,0x3ec6beed,0xbd493eed,0xbeff3e44,0xbe153efb,0xbef53dc8,0x3ee2bed5,0x3e713e8e,
0xbe8e3f00,0xbed50000,0x3ed50000,0xbe8e3f00,0x3efbbe44,0xbdc83eed,0x3dc8beed,0x3efbbe44,0xbdc8beb5,0x3efbbeb5,0xbefb3eb5,0xbdc8beb5,0xbed53eed,0xbe8ebe44,0x3e8e3e44,0xbed53eed,
0xbea23f00,0xbec60000,0x3d493eb5,0xbeff3eb5,0x3ee2bdc8,0xbe713efb,0x3ef5bed5,0x3e153e8e,0x3e15beed,0x3ef5be44,0xbe71be44,0x3ee2beed,0xbeff3e8e,0x3d49bed5,0xbec63efb,0xbea2bdc8,
0x3eb53f00,0xbeb50000,0x3eb53f00,0xbeb50000,0xbeb50000,0xbeb5bf00,0xbeb50000,0xbeb5bf00,0xbeb5bf00,0x3eb50000,0xbeb5bf00,0x3eb50000,0x3eb50000,0x3eb53f00,0x3eb50000,0x3eb53f00,
0xbeff3f00,0x3d490000,0xbea23eb5,0x3ec6beb5,0xbef53efb,0x3e15bdc8,0xbe713e8e,0x3ee2bed5,0xbee23eed,0x3e71be44,0xbe153e44,0x3ef5beed,0xbec63ed5,0x3ea2be8e,0xbd493dc8,0x3effbefb,
0xbefb3f00,0x3dc80000,0x3dc80000,0x3efbbf00,0xbed53eed,0x3e8ebe44,0x3e8ebe44,0x3ed5beed,0xbe8e3eb5,0x3ed5beb5,0x3ed5beb5,0x3e8ebeb5,0xbdc83e44,0x3efbbeed,0x3efbbeed,0x3dc8be44,
0xbef53f00,0x3e150000,0x3ee2beb5,0x3e71beb5,0xbea23ed5,0x3ec6be8e,0x3effbefb,0xbd49bdc8,0xbd493e44,0x3effbeed,0x3ec6beed,0xbea23e44,0x3e71bdc8,0x3ee2befb,0x3e15be8e,0xbef53ed5,
0xbeed3f00,0x3e440000,0x3eedbf00,0xbe440000,0xbe443eb5,0x3eedbeb5,0x3e44beb5,0xbeed3eb5,0x3e440000,0x3eedbf00,0xbe440000,0xbeed3f00,0x3eedbeb5,0x3e44beb5,0xbeed3eb5,0xbe443eb5,
0xbee23f00,0x3e710000,0x3e15beb5,0xbef53eb5,0xbd493e8e,0x3effbed5,0xbea23dc8,0xbec63efb,0x3ec6be44,0x3ea2beed,0xbeff3eed,0x3d493e44,0x3ef5befb,0xbe15bdc8,0xbe713ed5,0x3ee2be8e,
0xbed53f00,0x3e8e0000,0xbe8e0000,0xbed53f00,0x3dc83e44,0x3efbbeed,0xbefb3eed,0x3dc83e44,0x3efbbeb5,0x3dc8beb5,0xbdc83eb5,0x3efbbeb5,0x3e8ebeed,0xbed53e44,0x3ed5be44,0x3e8ebeed,
0xbec63f00,0x3ea20000,0xbeff3eb5,0xbd493eb5,0x3e713dc8,0x3ee2befb,0xbe153ed5,0x3ef5be8e,0x3ef5beed,0xbe15be44,0x3ee2be44,0x3e71beed,0xbd49be8e,0xbeff3ed5,0x3ea2befb,0xbec63dc8,
0xbeb53f00,0xbeb50000,0xbeb53f00,0xbeb50000,0x3eb50000,0xbeb53f00,0x3eb50000,0xbeb53f00,0x3eb5bf00,0x3eb50000,0x3eb5bf00,0x3eb50000,0xbeb50000,0x3eb5bf00,0xbeb50000,0x3eb5bf00,
0x3d493f00,0x3eff0000,0x3ec63eb5,0x3ea2beb5,0xbe15befb,0xbef53dc8,0xbee2be8e,0xbe713ed5,0x3e713eed,0x3ee2be44,0x3ef53e44,0x3e15beed,0xbea2bed5,0xbec63e8e,0xbeffbdc8,0xbd493efb,
0x3dc83f00,0x3efb0000,0x3efb0000,0xbdc8bf00,0xbe8ebeed,0xbed53e44,0xbed53e44,0x3e8e3eed,0x3ed53eb5,0x3e8ebeb5,0x3e8ebeb5,0xbed5beb5,0xbefbbe44,0xbdc83eed,0xbdc83eed,0x3efb3e44,
0x3e153f00,0x3ef50000,0x3e71beb5,0xbee2beb5,0xbec6bed5,0xbea23e8e,0x3d493efb,0x3eff3dc8,0x3eff3e44,0x3d49beed,0xbea2beed,0xbec63e44,0xbee23dc8,0x3e713efb,0x3ef53e8e,0x3e15bed5,
0x3e443f00,0x3eed0000,0xbe44bf00,0xbeed0000,0xbeedbeb5,0xbe443eb5,0x3eed3eb5,0x3e44beb5,0x3eed0000,0xbe44bf00,0xbeed0000,0x3e443f00,0xbe443eb5,0x3eed3eb5,0x3e44beb5,0xbeedbeb5,
0x3e713f00,0x3ee20000,0xbef5beb5,0xbe153eb5,0xbeffbe8e,0xbd493ed5,0x3ec6bdc8,0xbea2befb,0x3ea2be44,0xbec6beed,0x3d493eed,0x3eff3e44,0x3e153efb,0x3ef53dc8,0xbee2bed5,0xbe713e8e,
0x3e8e3f00,0x3ed50000,0xbed50000,0x3e8e3f00,0xbefbbe44,0x3dc83eed,0xbdc8beed,0xbefbbe44,0x3dc8beb5,0xbefbbeb5,0x3efb3eb5,0x3dc8beb5,0x3ed53eed,0x3e8ebe44,0xbe8e3e44,0x3ed53eed,
0x3ea23f00,0x3ec60000,0xbd493eb5,0x3eff3eb5,0xbee2bdc8,0x3e713efb,0xbef5bed5,0xbe153e8e,0xbe15beed,0xbef5be44,0x3e71be44,0xbee2beed,0x3eff3e8e,0xbd49bed5,0x3ec63efb,0x3ea2bdc8,
0x3f003f00,0xbf003f00,0x3f003f00,0xbf003f00,0x3f003f00,0xbf003f00,0x3f003f00,0xbf003f00,0x3f003f00,0xbf003f00,0x3f003f00,0xbf003f00,0x3f003f00,0xbf003f00,0x3f003f00,0xbf003f00,
0xbd490000,0xbeffbf00,0xbec6beb5,0xbea2beb5,0xbe15bdc8,0xbef5befb,0xbee2bed5,0xbe71be8e,0xbe71be44,0xbee2beed,0xbef5beed,0xbe15be44,0xbea2be8e,0xbec6bed5,0xbeffbefb,0xbd49bdc8,
0xbefbbf00,0x3dc80000,0x3dc80000,0x3efb3f00,0xbed5beed,0x3e8e3e44,0x3e8e3e44,0x3ed53eed,0xbe8ebeb5,0x3ed53eb5,0x3ed53eb5,0x3e8e3eb5,0xbdc8be44,0x3efb3eed,0x3efb3eed,0x3dc83e44,
0x3e150000,0x3ef53f00,0x3e713eb5,0xbee2beb5,0x3ec63e8e,0x3ea23ed5,0xbd493dc8,0xbeffbefb,0x3eff3eed,0x3d493e44,0xbea2be44,0xbec6beed,0x3ee23efb,0xbe71bdc8,0xbef5bed5,0xbe15be8e,
0x3eed3f00,0xbe440000,0xbeedbf00,0x3e440000,0x3e443eb5,0xbeedbeb5,0xbe44beb5,0x3eed3eb5,0xbe440000,0xbeedbf00,0x3e440000,0x3eed3f00,0xbeedbeb5,0xbe44beb5,0x3eed3eb5,0x3e443eb5,
0xbe710000,0xbee2bf00,0x3ef53eb5,0x3e153eb5,0xbeffbed5,0xbd49be8e,0x3ec63efb,0xbea2bdc8,0xbea2beed,0x3ec63e44,0xbd493e44,0xbeffbeed,0x3e15bdc8,0x3ef53efb,0xbee2be8e,0xbe71bed5,
0xbed5bf00,0x3e8e0000,0xbe8e0000,0xbed5bf00,0x3dc8be44,0x3efb3eed,0xbefbbeed,0x3dc8be44,0x3efb3eb5,0x3dc83eb5,0xbdc8beb5,0x3efb3eb5,0x3e8e3eed,0xbed5be44,0x3ed53e44,0x3e8e3eed,
0x3ea20000,0x3ec63f00,0xbd49beb5,0x3eff3eb5,0x3ee23efb,0xbe713dc8,0x3ef53e8e,0x3e153ed5,0xbe153e44,0xbef5beed,0x3e713eed,0xbee2be44,0xbeffbed5,0x3d49be8e,0xbec6bdc8,0xbea2befb,
0x3f00,0xbf000000,0x3f00,0xbf000000,0xbf00,0x3f000000,0xbf00,0x3f000000,0x3f00,0xbf000000,0x3f00,0xbf000000,0xbf00,0x3f000000,0xbf00,0x3f000000,
0xbeff0000,0x3d49bf00,0xbea2beb5,0x3ec6beb5,0x3ef53dc8,0xbe153efb,0x3e713ed5,0xbee23e8e,0xbee2be44,0x3e71beed,0xbe15beed,0x3ef5be44,0x3ec63e8e,0xbea23ed5,0x3d493efb,0xbeff3dc8,
0x3dc8bf00,0x3efb0000,0x3efb0000,0xbdc83f00,0xbe8e3eed,0xbed5be44,0xbed5be44,0x3e8ebeed,0x3ed5beb5,0x3e8e3eb5,0x3e8e3eb5,0xbed53eb5,0xbefb3e44,0xbdc8beed,0xbdc8beed,0x3efbbe44,
0x3ef50000,0xbe153f00,0xbee23eb5,0xbe71beb5,0xbea2be8e,0x3ec6bed5,0x3effbdc8,0xbd493efb,0x3d493eed,0xbeff3e44,0xbec6be44,0x3ea2beed,0x3e71befb,0x3ee23dc8,0x3e153ed5,0xbef53e8e,
0xbe443f00,0xbeed0000,0x3e44bf00,0x3eed0000,0x3eedbeb5,0x3e443eb5,0xbeed3eb5,0xbe44beb5,0xbeed0000,0x3e44bf00,0x3eed0000,0xbe443f00,0x3e443eb5,0xbeed3eb5,0xbe44beb5,0x3eedbeb5,
0xbee20000,0x3e71bf00,0x3e153eb5,0xbef53eb5,0x3d493ed5,0xbeff3e8e,0x3ea2befb,0x3ec63dc8,0x3ec6beed,0x3ea23e44,0xbeff3e44,0x3d49beed,0xbef53dc8,0x3e15befb,0x3e713e8e,0xbee23ed5,
0x3e8ebf00,0x3ed50000,0xbed50000,0x3e8ebf00,0xbefb3e44,0x3dc8beed,0xbdc83eed,0xbefb3e44,0x3dc83eb5,0xbefb3eb5,0x3efbbeb5,0x3dc83eb5,0x3ed5beed,0x3e8e3e44,0xbe8ebe44,0x3ed5beed,
0x3ec60000,0xbea23f00,0x3effbeb5,0x3d493eb5,0x3e71befb,0x3ee2bdc8,0xbe15be8e,0x3ef5bed5,0xbef53e44,0x3e15beed,0xbee23eed,0xbe71be44,0xbd493ed5,0xbeff3e8e,0x3ea23dc8,0xbec63efb,
0x3eb53f00,0xbeb50000,0x3eb53f00,0xbeb50000,0xbeb50000,0xbeb5bf00,0xbeb50000,0xbeb5bf00,0xbeb5bf00,0x3eb50000,0xbeb5bf00,0x3eb50000,0x3eb50000,0x3eb53f00,0x3eb50000,0x3eb53f00,
0x3d490000,0x3effbf00,0x3ec6beb5,0x3ea2beb5,0x3e15bdc8,0x3ef5befb,0x3ee2bed5,0x3e71be8e,0x3e71be44,0x3ee2beed,0x3ef5beed,0x3e15be44,0x3ea2be8e,0x3ec6bed5,0x3effbefb,0x3d49bdc8,
0x3efbbf00,0xbdc80000,0xbdc80000,0xbefb3f00,0x3ed5beed,0xbe8e3e44,0xbe8e3e44,0xbed53eed,0x3e8ebeb5,0xbed53eb5,0xbed53eb5,0xbe8e3eb5,0x3dc8be44,0xbefb3eed,0xbefb3eed,0xbdc83e44,
0xbe150000,0xbef53f00,0xbe713eb5,0x3ee2beb5,0xbec63e8e,0xbea23ed5,0x3d493dc8,0x3effbefb,0xbeff3eed,0xbd493e44,0x3ea2be44,0x3ec6beed,0xbee23efb,0x3e71bdc8,0x3ef5bed5,0x3e15be8e,
0xbeed3f00,0x3e440000,0x3eedbf00,0xbe440000,0xbe443eb5,0x3eedbeb5,0x3e44beb5,0xbeed3eb5,0x3e440000,0x3eedbf00,0xbe440000,0xbeed3f00,0x3eedbeb5,0x3e44beb5,0xbeed3eb5,0xbe443eb5,
0x3e710000,0x3ee2bf00,0xbef53eb5,0xbe153eb5,0x3effbed5,0x3d49be8e,0xbec63efb,0x3ea2bdc8,0x3ea2beed,0xbec63e44,0x3d493e44,0x3effbeed,0xbe15bdc8,0xbef53efb,0x3ee2be8e,0x3e71bed5,
0x3ed5bf00,0xbe8e0000,0x3e8e0000,0x3ed5bf00,0xbdc8be44,0xbefb3eed,0x3efbbeed,0xbdc8be44,0xbefb3eb5,0xbdc83eb5,0x3dc8beb5,0xbefb3eb5,0xbe8e3eed,0x3ed5be44,0xbed53e44,0xbe8e3eed,
0xbea20000,0xbec63f00,0x3d49beb5,0xbeff3eb5,0xbee23efb,0x3e713dc8,0xbef53e8e,0xbe153ed5,0x3e153e44,0x3ef5beed,0xbe713eed,0x3ee2be44,0x3effbed5,0xbd49be8e,0x3ec6bdc8,0x3ea2befb,
0xbeb53f00,0xbeb50000,0xbeb53f00,0xbeb50000,0x3eb50000,0xbeb53f00,0x3eb50000,0xbeb53f00,0x3eb5bf00,0x3eb50000,0x3eb5bf00,0x3eb50000,0xbeb50000,0x3eb5bf00,0xbeb50000,0x3eb5bf00,
0x3eff0000,0xbd49bf00,0x3ea2beb5,0xbec6beb5,0xbef53dc8,0x3e153efb,0xbe713ed5,0x3ee23e8e,0x3ee2be44,0xbe71beed,0x3e15beed,0xbef5be44,0xbec63e8e,0x3ea23ed5,0xbd493efb,0x3eff3dc8,
0xbdc8bf00,0xbefb0000,0xbefb0000,0x3dc83f00,0x3e8e3eed,0x3ed5be44,0x3ed5be44,0xbe8ebeed,0xbed5beb5,0xbe8e3eb5,0xbe8e3eb5,0x3ed53eb5,0x3efb3e44,0x3dc8beed,0x3dc8beed,0xbefbbe44,
0xbef50000,0x3e153f00,0x3ee23eb5,0x3e71beb5,0x3ea2be8e,0xbec6bed5,0xbeffbdc8,0x3d493efb,0xbd493eed,0x3eff3e44,0x3ec6be44,0xbea2beed,0xbe71befb,0xbee23dc8,0xbe153ed5,0x3ef53e8e,
0x3e443f00,0x3eed0000,0xbe44bf00,0xbeed0000,0xbeedbeb5,0xbe443eb5,0x3eed3eb5,0x3e44beb5,0x3eed0000,0xbe44bf00,0xbeed0000,0x3e443f00,0xbe443eb5,0x3eed3eb5,0x3e44beb5,0xbeedbeb5,
0x3ee20000,0xbe71bf00,0xbe153eb5,0x3ef53eb5,0xbd493ed5,0x3eff3e8e,0xbea2befb,0xbec63dc8,0xbec6beed,0xbea23e44,0x3eff3e44,0xbd49beed,0x3ef53dc8,0xbe15befb,0xbe713e8e,0x3ee23ed5,
0xbe8ebf00,0xbed50000,0x3ed50000,0xbe8ebf00,0x3efb3e44,0xbdc8beed,0x3dc83eed,0x3efb3e44,0xbdc83eb5,0x3efb3eb5,0xbefbbeb5,0xbdc83eb5,0xbed5beed,0xbe8e3e44,0x3e8ebe44,0xbed5beed,
0xbec60000,0x3ea23f00,0xbeffbeb5,0xbd493eb5,0xbe71befb,0xbee2bdc8,0x3e15be8e,0xbef5bed5,0x3ef53e44,0xbe15beed,0x3ee23eed,0x3e71be44,0x3d493ed5,0x3eff3e8e,0xbea23dc8,0x3ec63efb,
0x3f003f00,0xbf003f00,0x3f003f00,0xbf003f00,0x3f003f00,0xbf003f00,0x3f003f00,0xbf003f00,0x3f003f00,0xbf003f00,0x3f003f00,0xbf003f00,0x3f003f00,0xbf003f00,0x3f003f00,0xbf003f00,
0xbeffbf00,0x3d490000,0xbea2beb5,0x3ec63eb5,0xbef5befb,0x3e153dc8,0xbe71be8e,0x3ee23ed5,0xbee2beed,0x3e713e44,0xbe15be44,0x3ef53eed,0xbec6bed5,0x3ea23e8e,0xbd49bdc8,0x3eff3efb,
0x3efb3f00,0xbdc80000,0xbdc80000,0xbefbbf00,0x3ed53eed,0xbe8ebe44,0xbe8ebe44,0xbed5beed,0x3e8e3eb5,0xbed5beb5,0xbed5beb5,0xbe8ebeb5,0x3dc83e44,0xbefbbeed,0xbefbbeed,0xbdc8be44,
0xbef5bf00,0x3e150000,0x3ee23eb5,0x3e713eb5,0xbea2bed5,0x3ec63e8e,0x3eff3efb,0xbd493dc8,0xbd49be44,0x3eff3eed,0x3ec63eed,0xbea2be44,0x3e713dc8,0x3ee23efb,0x3e153e8e,0xbef5bed5,
0x3eed3f00,0xbe440000,0xbeedbf00,0x3e440000,0x3e443eb5,0xbeedbeb5,0xbe44beb5,0x3eed3eb5,0xbe440000,0xbeedbf00,0x3e440000,0x3eed3f00,0xbeedbeb5,0xbe44beb5,0x3eed3eb5,0x3e443eb5,
0xbee2bf00,0x3e710000,0x3e153eb5,0xbef5beb5,0xbd49be8e,0x3eff3ed5,0xbea2bdc8,0xbec6befb,0x3ec63e44,0x3ea23eed,0xbeffbeed,0x3d49be44,0x3ef53efb,0xbe153dc8,0xbe71bed5,0x3ee23e8e,
0x3ed53f00,0xbe8e0000,0x3e8e0000,0x3ed53f00,0xbdc83e44,0xbefbbeed,0x3efb3eed,0xbdc83e44,0xbefbbeb5,0xbdc8beb5,0x3dc83eb5,0xbefbbeb5,0xbe8ebeed,0x3ed53e44,0xbed5be44,0xbe8ebeed,
0xbec6bf00,0x3ea20000,0xbeffbeb5,0xbd49beb5,0x3e71bdc8,0x3ee23efb,0xbe15bed5,0x3ef53e8e,0x3ef53eed,0xbe153e44,0x3ee23e44,0x3e713eed,0xbd493e8e,0xbeffbed5,0x3ea23efb,0xbec6bdc8,
0x3f00,0xbf000000,0x3f00,0xbf000000,0xbf00,0x3f000000,0xbf00,0x3f000000,0x3f00,0xbf000000,0x3f00,0xbf000000,0xbf00,0x3f000000,0xbf00,0x3f000000,
0x3d49bf00,0x3eff0000,0x3ec6beb5,0x3ea23eb5,0xbe153efb,0xbef5bdc8,0xbee23e8e,0xbe71bed5,0x3e71beed,0x3ee23e44,0x3ef5be44,0x3e153eed,0xbea23ed5,0xbec6be8e,0xbeff3dc8,0xbd49befb,
0xbdc83f00,0xbefb0000,0xbefb0000,0x3dc8bf00,0x3e8ebeed,0x3ed53e44,0x3ed53e44,0xbe8e3eed,0xbed53eb5,0xbe8ebeb5,0xbe8ebeb5,0x3ed5beb5,0x3efbbe44,0x3dc83eed,0x3dc83eed,0xbefb3e44,
0x3e15bf00,0x3ef50000,0x3e713eb5,0xbee23eb5,0xbec63ed5,0xbea2be8e,0x3d49befb,0x3effbdc8,0x3effbe44,0x3d493eed,0xbea23eed,0xbec6be44,0xbee2bdc8,0x3e71befb,0x3ef5be8e,0x3e153ed5,
0xbe443f00,0xbeed0000,0x3e44bf00,0x3eed0000,0x3eedbeb5,0x3e443eb5,0xbeed3eb5,0xbe44beb5,0xbeed0000,0x3e44bf00,0x3eed0000,0xbe443f00,0x3e443eb5,0xbeed3eb5,0xbe44beb5,0x3eedbeb5,
0x3e71bf00,0x3ee20000,0xbef53eb5,0xbe15beb5,0xbeff3e8e,0xbd49bed5,0x3ec63dc8,0xbea23efb,0x3ea23e44,0xbec63eed,0x3d49beed,0x3effbe44,0x3e15befb,0x3ef5bdc8,0xbee23ed5,0xbe71be8e,
0xbe8e3f00,0xbed50000,0x3ed50000,0xbe8e3f00,0x3efbbe44,0xbdc83eed,0x3dc8beed,0x3efbbe44,0xbdc8beb5,0x3efbbeb5,0xbefb3eb5,0xbdc8beb5,0xbed53eed,0xbe8ebe44,0x3e8e3e44,0xbed53eed,
0x3ea2bf00,0x3ec60000,0xbd49beb5,0x3effbeb5,0xbee23dc8,0x3e71befb,0xbef53ed5,0xbe15be8e,0xbe153eed,0xbef53e44,0x3e713e44,0xbee23eed,0x3effbe8e,0xbd493ed5,0x3ec6befb,0x3ea23dc8,
0x3eb53f00,0xbeb50000,0x3eb53f00,0xbeb50000,0xbeb50000,0xbeb5bf00,0xbeb50000,0xbeb5bf00,0xbeb5bf00,0x3eb50000,0xbeb5bf00,0x3eb50000,0x3eb50000,0x3eb53f00,0x3eb50000,0x3eb53f00,
0x3effbf00,0xbd490000,0x3ea2beb5,0xbec63eb5,0x3ef5befb,0xbe153dc8,0x3e71be8e,0xbee23ed5,0x3ee2beed,0xbe713e44,0x3e15be44,0xbef53eed,0x3ec6bed5,0xbea23e8e,0x3d49bdc8,0xbeff3efb,
0xbefb3f00,0x3dc80000,0x3dc80000,0x3efbbf00,0xbed53eed,0x3e8ebe44,0x3e8ebe44,0x3ed5beed,0xbe8e3eb5,0x3ed5beb5,0x3ed5beb5,0x3e8ebeb5,0xbdc83e44,0x3efbbeed,0x3efbbeed,0x3dc8be44,
0x3ef5bf00,0xbe150000,0xbee23eb5,0xbe713eb5,0x3ea2bed5,0xbec63e8e,0xbeff3efb,0x3d493dc8,0x3d49be44,0xbeff3eed,0xbec63eed,0x3ea2be44,0xbe713dc8,0xbee23efb,0xbe153e8e,0x3ef5bed5,
0xbeed3f00,0x3e440000,0x3eedbf00,0xbe440000,0xbe443eb5,0x3eedbeb5,0x3e44beb5,0xbeed3eb5,0x3e440000,0x3eedbf00,0xbe440000,0xbeed3f00,0x3eedbeb5,0x3e44beb5,0xbeed3eb5,0xbe443eb5,
0x3ee2bf00,0xbe710000,0xbe153eb5,0x3ef5beb5,0x3d49be8e,0xbeff3ed5,0x3ea2bdc8,0x3ec6befb,0xbec63e44,0xbea23eed,0x3effbeed,0xbd49be44,0xbef53efb,0x3e153dc8,0x3e71bed5,0xbee23e8e,
0xbed53f00,0x3e8e0000,0xbe8e0000,0xbed53f00,0x3dc83e44,0x3efbbeed,0xbefb3eed,0x3dc83e44,0x3efbbeb5,0x3dc8beb5,0xbdc83eb5,0x3efbbeb5,0x3e8ebeed,0xbed53e44,0x3ed5be44,0x3e8ebeed,
0x3ec6bf00,0xbea20000,0x3effbeb5,0x3d49beb5,0xbe71bdc8,0xbee23efb,0x3e15bed5,0xbef53e8e,0xbef53eed,0x3e153e44,0xbee23e44,0xbe713eed,0x3d493e8e,0x3effbed5,0xbea23efb,0x3ec6bdc8,
0xbeb53f00,0xbeb50000,0xbeb53f00,0xbeb50000,0x3eb50000,0xbeb53f00,0x3eb50000,0xbeb53f00,0x3eb5bf00,0x3eb50000,0x3eb5bf00,0x3eb50000,0xbeb50000,0x3eb5bf00,0xbeb50000,0x3eb5bf00,
0xbd49bf00,0xbeff0000,0xbec6beb5,0xbea23eb5,0x3e153efb,0x3ef5bdc8,0x3ee23e8e,0x3e71bed5,0xbe71beed,0xbee23e44,0xbef5be44,0xbe153eed,0x3ea23ed5,0x3ec6be8e,0x3eff3dc8,0x3d49befb,
0x3dc83f00,0x3efb0000,0x3efb0000,0xbdc8bf00,0xbe8ebeed,0xbed53e44,0xbed53e44,0x3e8e3eed,0x3ed53eb5,0x3e8ebeb5,0x3e8ebeb5,0xbed5beb5,0xbefbbe44,0xbdc83eed,0xbdc83eed,0x3efb3e44,
0xbe15bf00,0xbef50000,0xbe713eb5,0x3ee23eb5,0x3ec63ed5,0x3ea2be8e,0xbd49befb,0xbeffbdc8,0xbeffbe44,0xbd493eed,0x3ea23eed,0x3ec6be44,0x3ee2bdc8,0xbe71befb,0xbef5be8e,0xbe153ed5,
0x3e443f00,0x3eed0000,0xbe44bf00,0xbeed0000,0xbeedbeb5,0xbe443eb5,0x3eed3eb5,0x3e44beb5,0x3eed0000,0xbe44bf00,0xbeed0000,0x3e443f00,0xbe443eb5,0x3eed3eb5,0x3e44beb5,0xbeedbeb5,
0xbe71bf00,0xbee20000,0x3ef53eb5,0x3e15beb5,0x3eff3e8e,0x3d49bed5,0xbec63dc8,0x3ea23efb,0xbea23e44,0x3ec63eed,0xbd49beed,0xbeffbe44,0xbe15befb,0xbef5bdc8,0x3ee23ed5,0x3e71be8e,
0x3e8e3f00,0x3ed50000,0xbed50000,0x3e8e3f00,0xbefbbe44,0x3dc83eed,0xbdc8beed,0xbefbbe44,0x3dc8beb5,0xbefbbeb5,0x3efb3eb5,0x3dc8beb5,0x3ed53eed,0x3e8ebe44,0xbe8e3e44,0x3ed53eed,
0xbea2bf00,0xbec60000,0x3d49beb5,0xbeffbeb5,0x3ee23dc8,0xbe71befb,0x3ef53ed5,0x3e15be8e,0x3e153eed,0x3ef53e44,0xbe713e44,0x3ee23eed,0xbeffbe8e,0x3d493ed5,0xbec6befb,0xbea23dc8,
0x3f003f00,0xbf003f00,0x3f003f00,0xbf003f00,0x3f003f00,0xbf003f00,0x3f003f00,0xbf003f00,0x3f003f00,0xbf003f00,0x3f003f00,0xbf003f00,0x3f003f00,0xbf003f00,0x3f003f00,0xbf003f00,
0x3d490000,0x3eff3f00,0x3ec63eb5,0x3ea23eb5,0x3e153dc8,0x3ef53efb,0x3ee23ed5,0x3e713e8e,0x3e713e44,0x3ee23eed,0x3ef53eed,0x3e153e44,0x3ea23e8e,0x3ec63ed5,0x3eff3efb,0x3d493dc8,
0xbefbbf00,0x3dc80000,0x3dc80000,0x3efb3f00,0xbed5beed,0x3e8e3e44,0x3e8e3e44,0x3ed53eed,0xbe8ebeb5,0x3ed53eb5,0x3ed53eb5,0x3e8e3eb5,0xbdc8be44,0x3efb3eed,0x3efb3eed,0x3dc83e44,
0xbe150000,0xbef5bf00,0xbe71beb5,0x3ee23eb5,0xbec6be8e,0xbea2bed5,0x3d49bdc8,0x3eff3efb,0xbeffbeed,0xbd49be44,0x3ea23e44,0x3ec63eed,0xbee2befb,0x3e713dc8,0x3ef53ed5,0x3e153e8e,
0x3eed3f00,0xbe440000,0xbeedbf00,0x3e440000,0x3e443eb5,0xbeedbeb5,0xbe44beb5,0x3eed3eb5,0xbe440000,0xbeedbf00,0x3e440000,0x3eed3f00,0xbeedbeb5,0xbe44beb5,0x3eed3eb5,0x3e443eb5,
0x3e710000,0x3ee23f00,0xbef5beb5,0xbe15beb5,0x3eff3ed5,0x3d493e8e,0xbec6befb,0x3ea23dc8,0x3ea23eed,0xbec6be44,0x3d49be44,0x3eff3eed,0xbe153dc8,0xbef5befb,0x3ee23e8e,0x3e713ed5,
0xbed5bf00,0x3e8e0000,0xbe8e0000,0xbed5bf00,0x3dc8be44,0x3efb3eed,0xbefbbeed,0x3dc8be44,0x3efb3eb5,0x3dc83eb5,0xbdc8beb5,0x3efb3eb5,0x3e8e3eed,0xbed5be44,0x3ed53e44,0x3e8e3eed,
0xbea20000,0xbec6bf00,0x3d493eb5,0xbeffbeb5,0xbee2befb,0x3e71bdc8,0xbef5be8e,0xbe15bed5,0x3e15be44,0x3ef53eed,0xbe71beed,0x3ee23e44,0x3eff3ed5,0xbd493e8e,0x3ec63dc8,0x3ea23efb,
0x3f00,0xbf000000,0x3f00,0xbf000000,0xbf00,0x3f000000,0xbf00,0x3f000000,0x3f00,0xbf000000,0x3f00,0xbf000000,0xbf00,0x3f000000,0xbf00,0x3f000000,
0x3eff0000,0xbd493f00,0x3ea23eb5,0xbec63eb5,0xbef5bdc8,0x3e15befb,0xbe71bed5,0x3ee2be8e,0x3ee23e44,0xbe713eed,0x3e153eed,0xbef53e44,0xbec6be8e,0x3ea2bed5,0xbd49befb,0x3effbdc8,
0x3dc8bf00,0x3efb0000,0x3efb0000,0xbdc83f00,0xbe8e3eed,0xbed5be44,0xbed5be44,0x3e8ebeed,0x3ed5beb5,0x3e8e3eb5,0x3e8e3eb5,0xbed53eb5,0xbefb3e44,0xbdc8beed,0xbdc8beed,0x3efbbe44,
0xbef50000,0x3e15bf00,0x3ee2beb5,0x3e713eb5,0x3ea23e8e,0xbec63ed5,0xbeff3dc8,0x3d49befb,0xbd49beed,0x3effbe44,0x3ec63e44,0xbea23eed,0xbe713efb,0xbee2bdc8,0xbe15bed5,0x3ef5be8e,
0xbe443f00,0xbeed0000,0x3e44bf00,0x3eed0000,0x3eedbeb5,0x3e443eb5,0xbeed3eb5,0xbe44beb5,0xbeed0000,0x3e44bf00,0x3eed0000,0xbe443f00,0x3e443eb5,0xbeed3eb5,0xbe44beb5,0x3eedbeb5,
0x3ee20000,0xbe713f00,0xbe15beb5,0x3ef5beb5,0xbd49bed5,0x3effbe8e,0xbea23efb,0xbec6bdc8,0xbec63eed,0xbea2be44,0x3effbe44,0xbd493eed,0x3ef5bdc8,0xbe153efb,0xbe71be8e,0x3ee2bed5,
0x3e8ebf00,0x3ed50000,0xbed50000,0x3e8ebf00,0xbefb3e44,0x3dc8beed,0xbdc83eed,0xbefb3e44,0x3dc83eb5,0xbefb3eb5,0x3efbbeb5,0x3dc83eb5,0x3ed5beed,0x3e8e3e44,0xbe8ebe44,0x3ed5beed,
0xbec60000,0x3ea2bf00,0xbeff3eb5,0xbd49beb5,0xbe713efb,0xbee23dc8,0x3e153e8e,0xbef53ed5,0x3ef5be44,0xbe153eed,0x3ee2beed,0x3e713e44,0x3d49bed5,0x3effbe8e,0xbea2bdc8,0x3ec6befb,
0x3eb53f00,0xbeb50000,0x3eb53f00,0xbeb50000,0xbeb50000,0xbeb5bf00,0xbeb50000,0xbeb5bf00,0xbeb5bf00,0x3eb50000,0xbeb5bf00,0x3eb50000,0x3eb50000,0x3eb53f00,0x3eb50000,0x3eb53f00,
0xbd490000,0xbeff3f00,0xbec63eb5,0xbea23eb5,0xbe153dc8,0xbef53efb,0xbee23ed5,0xbe713e8e,0xbe713e44,0xbee23eed,0xbef53eed,0xbe153e44,0xbea23e8e,0xbec63ed5,0xbeff3efb,0xbd493dc8,
0x3efbbf00,0xbdc80000,0xbdc80000,0xbefb3f00,0x3ed5beed,0xbe8e3e44,0xbe8e3e44,0xbed53eed,0x3e8ebeb5,0xbed53eb5,0xbed53eb5,0xbe8e3eb5,0x3dc8be44,0xbefb3eed,0xbefb3eed,0xbdc83e44,
0x3e150000,0x3ef5bf00,0x3e71beb5,0xbee23eb5,0x3ec6be8e,0x3ea2bed5,0xbd49bdc8,0xbeff3efb,0x3effbeed,0x3d49be44,0xbea23e44,0xbec63eed,0x3ee2befb,0xbe713dc8,0xbef53ed5,0xbe153e8e,
0xbeed3f00,0x3e440000,0x3eedbf00,0xbe440000,0xbe443eb5,0x3eedbeb5,0x3e44beb5,0xbeed3eb5,0x3e440000,0x3eedbf00,0xbe440000,0xbeed3f00,0x3eedbeb5,0x3e44beb5,0xbeed3eb5,0xbe443eb5,
0xbe710000,0xbee23f00,0x3ef5beb5,0x3e15beb5,0xbeff3ed5,0xbd493e8e,0x3ec6befb,0xbea23dc8,0xbea23eed,0x3ec6be44,0xbd49be44,0xbeff3eed,0x3e153dc8,0x3ef5befb,0xbee23e8e,0xbe713ed5,
0x3ed5bf00,0xbe8e0000,0x3e8e0000,0x3ed5bf00,0xbdc8be44,0xbefb3eed,0x3efbbeed,0xbdc8be44,0xbefb3eb5,0xbdc83eb5,0x3dc8beb5,0xbefb3eb5,0xbe8e3eed,0x3ed5be44,0xbed53e44,0xbe8e3eed,
0x3ea20000,0x3ec6bf00,0xbd493eb5,0x3effbeb5,0x3ee2befb,0xbe71bdc8,0x3ef5be8e,0x3e15bed5,0xbe15be44,0xbef53eed,0x3e71beed,0xbee23e44,0xbeff3ed5,0x3d493e8e,0xbec63dc8,0xbea23efb,
0xbeb53f00,0xbeb50000,0xbeb53f00,0xbeb50000,0x3eb50000,0xbeb53f00,0x3eb50000,0xbeb53f00,0x3eb5bf00,0x3eb50000,0x3eb5bf00,0x3eb50000,0xbeb50000,0x3eb5bf00,0xbeb50000,0x3eb5bf00,
0xbeff0000,0x3d493f00,0xbea23eb5,0x3ec63eb5,0x3ef5bdc8,0xbe15befb,0x3e71bed5,0xbee2be8e,0xbee23e44,0x3e713eed,0xbe153eed,0x3ef53e44,0x3ec6be8e,0xbea2bed5,0x3d49befb,0xbeffbdc8,
0xbdc8bf00,0xbefb0000,0xbefb0000,0x3dc83f00,0x3e8e3eed,0x3ed5be44,0x3ed5be44,0xbe8ebeed,0xbed5beb5,0xbe8e3eb5,0xbe8e3eb5,0x3ed53eb5,0x3efb3e44,0x3dc8beed,0x3dc8beed,0xbefbbe44,
0x3ef50000,0xbe15bf00,0xbee2beb5,0xbe713eb5,0xbea23e8e,0x3ec63ed5,0x3eff3dc8,0xbd49befb,0x3d49beed,0xbeffbe44,0xbec63e44,0x3ea23eed,0x3e713efb,0x3ee2bdc8,0x3e15bed5,0xbef5be8e,
0x3e443f00,0x3eed0000,0xbe44bf00,0xbeed0000,0xbeedbeb5,0xbe443eb5,0x3eed3eb5,0x3e44beb5,0x3eed0000,0xbe44bf00,0xbeed0000,0x3e443f00,0xbe443eb5,0x3eed3eb5,0x3e44beb5,0xbeedbeb5,
0xbee20000,0x3e713f00,0x3e15beb5,0xbef5beb5,0x3d49bed5,0xbeffbe8e,0x3ea23efb,0x3ec6bdc8,0x3ec63eed,0x3ea2be44,0xbeffbe44,0x3d493eed,0xbef5bdc8,0x3e153efb,0x3e71be8e,0xbee2bed5,
0xbe8ebf00,0xbed50000,0x3ed50000,0xbe8ebf00,0x3efb3e44,0xbdc8beed,0x3dc83eed,0x3efb3e44,0xbdc83eb5,0x3efb3eb5,0xbefbbeb5,0xbdc83eb5,0xbed5beed,0xbe8e3e44,0x3e8ebe44,0xbed5beed,
0x3ec60000,0xbea2bf00,0x3eff3eb5,0x3d49beb5,0x3e713efb,0x3ee23dc8,0xbe153e8e,0x3ef53ed5,0xbef5be44,0x3e153eed,0xbee2beed,0xbe713e44,0xbd49bed5,0xbeffbe8e,0x3ea2bdc8,0xbec6befb,
0x3e00,0x3e00,0x3e00,0x3e00,0x3e00,0x3e00,0x3e00,0x3e00,0x3e00,0x3e00,0x3e00,0x3e00,0x3e00,0x3e00,0x3e00,0x3e00,
0xbd443ded,0xbcc83dfb,0xbc493dff,0xbd153df5,0xbdb53db5,0xbdd53d8e,0xbdc63da2,0xbde23d71,0xbe000000,0xbdfbbcc8,0xbdffbc49,0xbdf5bd15,0xbdb5bdb5,0xbd8ebdd5,0xbda2bdc6,0xbd71bde2,
0xbdb53db5,0xbd443ded,0xbcc83dfb,0xbd8e3dd5,0xbe000000,0xbdedbd44,0xbdfbbcc8,0xbdd5bd8e,0xbe00,0x3d44bded,0x3cc8bdfb,0x3d8ebdd5,0x3e000000,0x3ded3d44,0x3dfb3cc8,0x3dd53d8e,
0xbded3d44,0xbd8e3dd5,0xbd153df5,0xbdc63da2,0xbdb5bdb5,0xbcc8bdfb,0xbd71bde2,0x3c49bdff,0x3e000000,0x3dd53d8e,0x3df53d15,0x3da23dc6,0xbdb53db5,0xbdfb3cc8,0xbde23d71,0xbdffbc49,
0xbe000000,0xbdb53db5,0xbd443ded,0xbded3d44,0xbe00,0x3db5bdb5,0x3d44bded,0x3dedbd44,0x3e00,0xbdb53db5,0xbd443ded,0xbded3d44,0xbe00,0x3db5bdb5,0x3d44bded,0x3dedbd44,
0xbdedbd44,0xbdd53d8e,0xbd713de2,0xbdff3c49,0x3db5bdb5,0x3dfb3cc8,0x3df5bd15,0x3dc63da2,0xbe000000,0xbd8ebdd5,0xbde2bd71,0xbc49bdff,0x3db53db5,0xbcc83dfb,0x3d153df5,0xbda23dc6,
0xbdb5bdb5,0xbded3d44,0xbd8e3dd5,0xbdfbbcc8,0x3e000000,0x3d443ded,0x3dd53d8e,0xbcc83dfb,0xbe00,0x3dedbd44,0x3d8ebdd5,0x3dfb3cc8,0xbe000000,0xbd44bded,0xbdd5bd8e,0x3cc8bdfb,
0xbd44bded,0xbdfb3cc8,0xbda23dc6,0xbde2bd71,0x3db53db5,0xbd8e3dd5,0x3c493dff,0xbdf53d15,0x3e000000,0x3cc83dfb,0x3dc63da2,0xbd713de2,0x3db5bdb5,0x3dd53d8e,0x3dffbc49,0x3d153df5,
0xbe00,0xbe000000,0xbdb53db5,0xbdb5bdb5,0x3e00,0xbe000000,0xbdb53db5,0xbdb5bdb5,0x3e00,0xbe000000,0xbdb53db5,0xbdb5bdb5,0x3e00,0xbe000000,0xbdb53db5,0xbdb5bdb5,
0x3d44bded,0xbdfbbcc8,0xbdc63da2,0xbd71bde2,0xbdb53db5,0xbd8ebdd5,0xbdffbc49,0x3d15bdf5,0xbe000000,0x3cc8bdfb,0xbda2bdc6,0x3de2bd71,0xbdb5bdb5,0x3dd5bd8e,0x3c49bdff,0x3df53d15,
0x3db5bdb5,0xbdedbd44,0xbdd53d8e,0xbcc8bdfb,0xbe000000,0x3d44bded,0xbd8ebdd5,0x3dfbbcc8,0xbe00,0x3ded3d44,0x3dd5bd8e,0x3cc83dfb,0x3e000000,0xbd443ded,0x3d8e3dd5,0xbdfb3cc8,
0x3dedbd44,0xbdd5bd8e,0xbde23d71,0x3c49bdff,0xbdb5bdb5,0x3dfbbcc8,0x3d15bdf5,0x3da23dc6,0x3e000000,0xbd8e3dd5,0x3d713de2,0xbdffbc49,0xbdb53db5,0xbcc8bdfb,0xbdf5bd15,0x3dc6bda2,
0x3e000000,0xbdb5bdb5,0xbded3d44,0x3d44bded,0xbe00,0x3db53db5,0x3dedbd44,0xbd443ded,0x3e00,0xbdb5bdb5,0xbded3d44,0x3d44bded,0xbe00,0x3db53db5,0x3dedbd44,0xbd443ded,
0x3ded3d44,0xbd8ebdd5,0xbdf53d15,0x3da2bdc6,0x3db5bdb5,0xbcc83dfb,0x3de23d71,0xbdff3c49,0xbe000000,0x3dd5bd8e,0xbd15bdf5,0x3dc63da2,0x3db53db5,0xbdfbbcc8,0xbd713de2,0xbc49bdff,
0x3db53db5,0xbd44bded,0xbdfb3cc8,0x3dd5bd8e,0x3e000000,0xbded3d44,0x3cc83dfb,0xbd8ebdd5,0xbe00,0x3d443ded,0x3dfbbcc8,0xbdd53d8e,0xbe000000,0x3dedbd44,0xbcc8bdfb,0x3d8e3dd5,
0x3d443ded,0xbcc8bdfb,0xbdff3c49,0x3df5bd15,0x3db53db5,0xbdd5bd8e,0xbda23dc6,0x3d71bde2,0x3e000000,0xbdfb3cc8,0x3c493dff,0xbd15bdf5,0x3db5bdb5,0xbd8e3dd5,0x3dc63da2,0xbde2bd71,
0x3e00,0xbe00,0xbe000000,0x3e000000,0x3e00,0xbe00,0xbe000000,0x3e000000,0x3e00,0xbe00,0xbe000000,0x3e000000,0x3e00,0xbe00,0xbe000000,0x3e000000,
0xbd443ded,0x3cc8bdfb,0xbdffbc49,0x3df53d15,0xbdb53db5,0x3dd5bd8e,0xbda2bdc6,0x3d713de2,0xbe000000,0x3dfb3cc8,0x3c49bdff,0xbd153df5,0xbdb5bdb5,0x3d8e3dd5,0x3dc6bda2,0xbde23d71,
0xbdb53db5,0x3d44bded,0xbdfbbcc8,0x3dd53d8e,0xbe000000,0x3ded3d44,0x3cc8bdfb,0xbd8e3dd5,0xbe00,0xbd443ded,0x3dfb3cc8,0xbdd5bd8e,0x3e000000,0xbdedbd44,0xbcc83dfb,0x3d8ebdd5,
0xbded3d44,0x3d8ebdd5,0xbdf5bd15,0x3da23dc6,0xbdb5bdb5,0x3cc83dfb,0x3de2bd71,0xbdffbc49,0x3e000000,0xbdd5bd8e,0xbd153df5,0x3dc6bda2,0xbdb53db5,0x3dfbbcc8,0xbd71bde2,0xbc493dff,
0xbe000000,0x3db5bdb5,0xbdedbd44,0x3d443ded,0xbe00,0xbdb53db5,0x3ded3d44,0xbd44bded,0x3e00,0x3db5bdb5,0xbdedbd44,0x3d443ded,0xbe00,0xbdb53db5,0x3ded3d44,0xbd44bded,
0xbdedbd44,0x3dd5bd8e,0xbde2bd71,0x3c493dff,0x3db5bdb5,0xbdfbbcc8,0x3d153df5,0x3da2bdc6,0xbe000000,0x3d8e3dd5,0x3d71bde2,0xbdff3c49,0x3db53db5,0x3cc8bdfb,0xbdf53d15,0x3dc63da2,
0xbdb5bdb5,0x3dedbd44,0xbdd5bd8e,0xbcc83dfb,0x3e000000,0xbd44bded,0xbd8e3dd5,0x3dfb3cc8,0xbe00,0xbded3d44,0x3dd53d8e,0x3cc8bdfb,0xbe000000,0x3d443ded,0x3d8ebdd5,0xbdfbbcc8,
0xbd44bded,0x3dfbbcc8,0xbdc6bda2,0xbd713de2,0x3db53db5,0x3d8ebdd5,0xbdff3c49,0x3d153df5,0x3e000000,0xbcc8bdfb,0xbda23dc6,0x3de23d71,0x3db5bdb5,0xbdd5bd8e,0x3c493dff,0x3df5bd15,
0xbe00,0x3e000000,0xbdb5bdb5,0xbdb53db5,0x3e00,0x3e000000,0xbdb5bdb5,0xbdb53db5,0x3e00,0x3e000000,0xbdb5bdb5,0xbdb53db5,0x3e00,0x3e000000,0xbdb5bdb5,0xbdb53db5,
0x3d44bded,0x3dfb3cc8,0xbda2bdc6,0xbde23d71,0xbdb53db5,0x3d8e3dd5,0x3c49bdff,0xbdf5bd15,0xbe000000,0xbcc83dfb,0x3dc6bda2,0xbd71bde2,0xbdb5bdb5,0xbdd53d8e,0x3dff3c49,0x3d15bdf5,
0x3db5bdb5,0x3ded3d44,0xbd8ebdd5,0xbdfb3cc8,0xbe000000,0xbd443ded,0x3dd5bd8e,0xbcc8bdfb,0xbe00,0xbdedbd44,0x3d8e3dd5,0x3dfbbcc8,0x3e000000,0x3d44bded,0xbdd53d8e,0x3cc83dfb,
0x3dedbd44,0x3dd53d8e,0xbd71bde2,0xbdffbc49,0xbdb5bdb5,0xbdfb3cc8,0x3df53d15,0x3dc6bda2,0x3e000000,0x3d8ebdd5,0xbde23d71,0xbc493dff,0xbdb53db5,0x3cc83dfb,0x3d15bdf5,0xbda2bdc6,
0x3e000000,0x3db53db5,0xbd44bded,0xbdedbd44,0xbe00,0xbdb5bdb5,0x3d443ded,0x3ded3d44,0x3e00,0x3db53db5,0xbd44bded,0xbdedbd44,0xbe00,0xbdb5bdb5,0x3d443ded,0x3ded3d44,
0x3ded3d44,0x3d8e3dd5,0xbd15bdf5,0xbdc6bda2,0x3db5bdb5,0x3cc8bdfb,0xbd713de2,0x3c493dff,0xbe000000,0xbdd53d8e,0x3df5bd15,0x3da2bdc6,0x3db53db5,0x3dfb3cc8,0xbde2bd71,0xbdff3c49,
0x3db53db5,0x3d443ded,0xbcc8bdfb,0xbd8ebdd5,0x3e000000,0x3dedbd44,0xbdfb3cc8,0xbdd53d8e,0xbe00,0xbd44bded,0x3cc83dfb,0x3d8e3dd5,0xbe000000,0xbded3d44,0x3dfbbcc8,0x3dd5bd8e,
0x3d443ded,0x3cc83dfb,0xbc49bdff,0xbd15bdf5,0x3db53db5,0x3dd53d8e,0xbdc6bda2,0xbde2bd71,0x3e000000,0x3dfbbcc8,0xbdff3c49,0xbdf53d15,0x3db5bdb5,0x3d8ebdd5,0xbda23dc6,0xbd713de2,
0x3d803d80,0x3e00,0x3e00,0x3e00,0x3e00,0x3e00,0x3e00,0x3e00,0x3e00,0x3e00,0x3e00,0x3e00,0x3e00,0x3e00,0x3e00,0x3e00,
0xbd803d80,0x3cc8bdfb,0x3c49bdff,0x3d15bdf5,0xbded3d44,0x3dd5bd8e,0x3dc6bda2,0x3de2bd71,0xbdedbd44,0x3dfb3cc8,0x3dff3c49,0x3df53d15,0xbd44bded,0x3d8e3dd5,0x3da23dc6,0x3d713de2,
0x3d803d80,0xbd443ded,0xbcc83dfb,0xbd8e3dd5,0xbdb5bdb5,0xbdedbd44,0xbdfbbcc8,0xbdd5bd8e,0x3db5bdb5,0x3d44bded,0x3cc8bdfb,0x3d8ebdd5,0x3db53db5,0x3ded3d44,0x3dfb3cc8,0x3dd53d8e,
0xbd803d80,0x3d8ebdd5,0x3d15bdf5,0x3dc6bda2,0x3d44bded,0x3cc83dfb,0x3d713de2,0xbc493dff,0x3d443ded,0xbdd5bd8e,0xbdf5bd15,0xbda2bdc6,0xbdedbd44,0x3dfbbcc8,0x3de2bd71,0x3dff3c49,
0x3d803d80,0xbdb53db5,0xbd443ded,0xbded3d44,0x3e000000,0x3db5bdb5,0x3d44bded,0x3dedbd44,0xbe000000,0xbdb53db5,0xbd443ded,0xbded3d44,0x3e000000,0x3db5bdb5,0x3d44bded,0x3dedbd44,
0xbd803d80,0x3dd5bd8e,0x3d71bde2,0x3dffbc49,0x3d443ded,0xbdfbbcc8,0xbdf53d15,0xbdc6bda2,0x3d44bded,0x3d8e3dd5,0x3de23d71,0x3c493dff,0xbded3d44,0x3cc8bdfb,0xbd15bdf5,0x3da2bdc6,
0x3d803d80,0xbded3d44,0xbd8e3dd5,0xbdfbbcc8,0xbdb53db5,0x3d443ded,0x3dd53d8e,0xbcc83dfb,0x3db53db5,0x3dedbd44,0x3d8ebdd5,0x3dfb3cc8,0x3db5bdb5,0xbd44bded,0xbdd5bd8e,0x3cc8bdfb,
0xbd803d80,0x3dfbbcc8,0x3da2bdc6,0x3de23d71,0xbdedbd44,0x3d8ebdd5,0xbc49bdff,0x3df5bd15,0xbded3d44,0xbcc8bdfb,0xbdc6bda2,0x3d71bde2,0xbd443ded,0xbdd5bd8e,0xbdff3c49,0xbd15bdf5,
0x3d803d80,0xbe000000,0xbdb53db5,0xbdb5bdb5,0xbe00,0xbe000000,0xbdb53db5,0xbdb5bdb5,0xbe00,0xbe000000,0xbdb53db5,0xbdb5bdb5,0xbe00,0xbe000000,0xbdb53db5,0xbdb5bdb5,
0xbd803d80,0x3dfb3cc8,0x3dc6bda2,0x3d713de2,0x3dedbd44,0x3d8e3dd5,0x3dff3c49,0xbd153df5,0x3ded3d44,0xbcc83dfb,0x3da23dc6,0xbde23d71,0x3d443ded,0xbdd53d8e,0xbc493dff,0xbdf5bd15,
0x3d803d80,0xbdedbd44,0xbdd53d8e,0xbcc8bdfb,0x3db53db5,0x3d44bded,0xbd8ebdd5,0x3dfbbcc8,0xbdb53db5,0x3ded3d44,0x3dd5bd8e,0x3cc83dfb,0xbdb5bdb5,0xbd443ded,0x3d8e3dd5,0xbdfb3cc8,
0xbd803d80,0x3dd53d8e,0x3de2bd71,0xbc493dff,0xbd443ded,0xbdfb3cc8,0xbd153df5,0xbda2bdc6,0xbd44bded,0x3d8ebdd5,0xbd71bde2,0x3dff3c49,0x3ded3d44,0x3cc83dfb,0x3df53d15,0xbdc63da2,
0x3d803d80,0xbdb5bdb5,0xbded3d44,0x3d44bded,0xbe000000,0x3db53db5,0x3dedbd44,0xbd443ded,0x3e000000,0xbdb5bdb5,0xbded3d44,0x3d44bded,0xbe000000,0x3db53db5,0x3dedbd44,0xbd443ded,
0xbd803d80,0x3d8e3dd5,0x3df5bd15,0xbda23dc6,0xbd44bded,0x3cc8bdfb,0xbde2bd71,0x3dffbc49,0xbd443ded,0xbdd53d8e,0x3d153df5,0xbdc6bda2,0x3dedbd44,0x3dfb3cc8,0x3d71bde2,0x3c493dff,
0x3d803d80,0xbd44bded,0xbdfb3cc8,0x3dd5bd8e,0x3db5bdb5,0xbded3d44,0x3cc83dfb,0xbd8ebdd5,0xbdb5bdb5,0x3d443ded,0x3dfbbcc8,0xbdd53d8e,0xbdb53db5,0x3dedbd44,0xbcc8bdfb,0x3d8e3dd5,
0xbd803d80,0x3cc83dfb,0x3dffbc49,0xbdf53d15,0x3ded3d44,0x3dd53d8e,0x3da2bdc6,0xbd713de2,0x3dedbd44,0x3dfbbcc8,0xbc49bdff,0x3d153df5,0x3d44bded,0x3d8ebdd5,0xbdc6bda2,0x3de23d71,
0x3d803d80,0xbe00,0xbe000000,0x3e000000,0x3e00,0xbe00,0xbe000000,0x3e000000,0x3e00,0xbe00,0xbe000000,0x3e000000,0x3e00,0xbe00,0xbe000000,0x3e000000,
0xbd803d80,0xbcc83dfb,0x3dff3c49,0xbdf5bd15,0xbded3d44,0xbdd53d8e,0x3da23dc6,0xbd71bde2,0xbdedbd44,0xbdfbbcc8,0xbc493dff,0x3d15bdf5,0xbd44bded,0xbd8ebdd5,0xbdc63da2,0x3de2bd71,
0x3d803d80,0x3d44bded,0xbdfbbcc8,0x3dd53d8e,0xbdb5bdb5,0x3ded3d44,0x3cc8bdfb,0xbd8e3dd5,0x3db5bdb5,0xbd443ded,0x3dfb3cc8,0xbdd5bd8e,0x3db53db5,0xbdedbd44,0xbcc83dfb,0x3d8ebdd5,
0xbd803d80,0xbd8e3dd5,0x3df53d15,0xbda2bdc6,0x3d44bded,0xbcc8bdfb,0xbde23d71,0x3dff3c49,0x3d443ded,0x3dd53d8e,0x3d15bdf5,0xbdc63da2,0xbdedbd44,0xbdfb3cc8,0x3d713de2,0x3c49bdff,
0x3d803d80,0x3db5bdb5,0xbdedbd44,0x3d443ded,0x3e000000,0xbdb53db5,0x3ded3d44,0xbd44bded,0xbe000000,0x3db5bdb5,0xbdedbd44,0x3d443ded,0x3e000000,0xbdb53db5,0x3ded3d44,0xbd44bded,
0xbd803d80,0xbdd53d8e,0x3de23d71,0xbc49bdff,0x3d443ded,0x3dfb3cc8,0xbd15bdf5,0xbda23dc6,0x3d44bded,0xbd8ebdd5,0xbd713de2,0x3dffbc49,0xbded3d44,0xbcc83dfb,0x3df5bd15,0xbdc6bda2,
0x3d803d80,0x3dedbd44,0xbdd5bd8e,0xbcc83dfb,0xbdb53db5,0xbd44bded,0xbd8e3dd5,0x3dfb3cc8,0x3db53db5,0xbded3d44,0x3dd53d8e,0x3cc8bdfb,0x3db5bdb5,0x3d443ded,0x3d8ebdd5,0xbdfbbcc8,
0xbd803d80,0xbdfb3cc8,0x3dc63da2,0x3d71bde2,0xbdedbd44,0xbd8e3dd5,0x3dffbc49,0xbd15bdf5,0xbded3d44,0x3cc83dfb,0x3da2bdc6,0xbde2bd71,0xbd443ded,0x3dd53d8e,0xbc49bdff,0xbdf53d15,
0x3d803d80,0x3e000000,0xbdb5bdb5,0xbdb53db5,0xbe00,0x3e000000,0xbdb5bdb5,0xbdb53db5,0xbe00,0x3e000000,0xbdb5bdb5,0xbdb53db5,0xbe00,0x3e000000,0xbdb5bdb5,0xbdb53db5,
0xbd803d80,0xbdfbbcc8,0x3da23dc6,0x3de2bd71,0x3dedbd44,0xbd8ebdd5,0xbc493dff,0x3df53d15,0x3ded3d44,0x3cc8bdfb,0xbdc63da2,0x3d713de2,0x3d443ded,0x3dd5bd8e,0xbdffbc49,0xbd153df5,
0x3d803d80,0x3ded3d44,0xbd8ebdd5,0xbdfb3cc8,0x3db53db5,0xbd443ded,0x3dd5bd8e,0xbcc8bdfb,0xbdb53db5,0xbdedbd44,0x3d8e3dd5,0x3dfbbcc8,0xbdb5bdb5,0x3d44bded,0xbdd53d8e,0x3cc83dfb,
0xbd803d80,0xbdd5bd8e,0x3d713de2,0x3dff3c49,0xbd443ded,0x3dfbbcc8,0xbdf5bd15,0xbdc63da2,0xbd44bded,0xbd8e3dd5,0x3de2bd71,0x3c49bdff,0x3ded3d44,0xbcc8bdfb,0xbd153df5,0x3da23dc6,
0x3d803d80,0x3db53db5,0xbd44bded,0xbdedbd44,0xbe000000,0xbdb5bdb5,0x3d443ded,0x3ded3d44,0x3e000000,0x3db53db5,0xbd44bded,0xbdedbd44,0xbe000000,0xbdb5bdb5,0x3d443ded,0x3ded3d44,
0xbd803d80,0xbd8ebdd5,0x3d153df5,0x3dc63da2,0xbd44bded,0xbcc83dfb,0x3d71bde2,0xbc49bdff,0xbd443ded,0x3dd5bd8e,0xbdf53d15,0xbda23dc6,0x3dedbd44,0xbdfbbcc8,0x3de23d71,0x3dffbc49,
0x3d803d80,0x3d443ded,0xbcc8bdfb,0xbd8ebdd5,0x3db5bdb5,0x3dedbd44,0xbdfb3cc8,0xbdd53d8e,0xbdb5bdb5,0xbd44bded,0x3cc83dfb,0x3d8e3dd5,0xbdb53db5,0xbded3d44,0x3dfbbcc8,0x3dd5bd8e,
0xbd803d80,0xbcc8bdfb,0x3c493dff,0x3d153df5,0x3ded3d44,0xbdd5bd8e,0x3dc63da2,0x3de23d71,0x3dedbd44,0xbdfb3cc8,0x3dffbc49,0x3df5bd15,0x3d44bded,0xbd8e3dd5,0x3da2bdc6,0x3d71bde2,
0xbc493dff,0xbbc93e00,0xbb493e00,0xbc173dff,0xbcc83dfb,0xbcf93df8,0xbce03dfa,0xbd093df7,0xbd443ded,0xbd5b3de7,0xbd4f3dea,0xbd663de5,0xbd8e3dd5,0xbd983dce,0xbd933dd1,0xbd9d3dca,
0xbd713de2,0xbcf93df8,0xbc7b3dfe,0xbd383def,0xbdd53d8e,0xbdf13d2c,0xbde53d66,0xbdfa3ce0,0xbdedbd44,0xbdcebd98,0xbddfbd7c,0xbdb9bdb1,0xbcc8bdfb,0x3bc9be00,0xbc17bdff,0x3cafbdfc,
0xbdc63da2,0xbd5b3de7,0xbce03dfa,0xbd9d3dca,0xbdfbbcc8,0xbdcebd98,0xbdeabd4f,0xbda7bdc2,0x3d44bded,0x3dbebdac,0x3d93bdd1,0x3ddfbd7c,0x3dd53d8e,0x3d843ddc,0x3db13db9,0x3d213df3,
0xbdf53d15,0xbd983dce,0xbd213df3,0xbdd13d93,0xbd8ebdd5,0x3bc9be00,0xbd09bdf7,0x3d38bdef,0x3ded3d44,0x3d843ddc,0x3dc23da7,0x3ce03dfa,0xbdfb3cc8,0xbde7bd5b,0xbdfebc7b,0xbdb9bdb1,
0xbdffbc49,0xbdbe3dac,0xbd4f3dea,0xbdf33d21,0x3cc8bdfb,0x3ddcbd84,0x3d93bdd1,0x3dfebc7b,0xbd443ded,0xbdf13d2c,0xbdb93db1,0xbdffbc17,0x3d8ebdd5,0x3dfdbc96,0x3dd8bd89,0x3df73d09,
0xbde2bd71,0xbddc3d84,0xbd7c3ddf,0xbe003b49,0x3dd5bd8e,0x3de73d5b,0x3dffbc17,0x3d933dd1,0xbdedbd44,0xbc96bdfd,0xbd9dbdca,0x3d38bdef,0x3cc83dfb,0xbdbe3dac,0xbd213df3,0xbdfa3ce0,
0xbda2bdc6,0xbdf13d2c,0xbd933dd1,0xbdf7bd09,0x3dfb3cc8,0x3c963dfd,0x3db13db9,0xbd663de5,0x3d44bded,0x3e003bc9,0x3dd8bd89,0x3dca3d9d,0xbdd5bd8e,0x3cf9bdf8,0xbd38bdef,0x3dc2bda7,
0xbd15bdf5,0xbdfd3c96,0xbda73dc2,0xbdd8bd89,0x3d8e3dd5,0xbdbe3dac,0xbc7b3dfe,0xbe003b49,0x3ded3d44,0xbcf93df8,0x3d663de5,0xbdd13d93,0x3dfbbcc8,0x3d2c3df1,0x3ddf3d7c,0xbd383def,
0x3c49bdff,0xbe00bbc9,0xbdb93db1,0xbda7bdc2,0xbcc83dfb,0xbdf8bcf9,0xbdd83d89,0xbd7cbddf,0xbd443ded,0xbde7bd5b,0xbdef3d38,0xbd21bdf3,0xbd8e3dd5,0xbdcebd98,0xbdfc3caf,0xbc7bbdfe,
0x3d71bde2,0xbdf8bcf9,0xbdca3d9d,0xbd4fbdea,0xbdd53d8e,0xbd2cbdf1,0xbdf3bd21,0x3d89bdd8,0xbdedbd44,0x3d98bdce,0xbd09bdf7,0x3e00bb49,0xbcc8bdfb,0x3e003bc9,0x3da7bdc2,0x3d933dd1,
0x3dc6bda2,0xbde7bd5b,0xbdd83d89,0xbc7bbdfe,0xbdfbbcc8,0x3d98bdce,0xbd38bdef,0x3dff3c17,0x3d44bded,0x3dac3dbe,0x3dfcbcaf,0xbd093df7,0x3dd53d8e,0xbddc3d84,0xbb493e00,0xbde5bd66,
0x3df5bd15,0xbdcebd98,0xbde53d66,0x3cafbdfc,0xbd8ebdd5,0x3e003bc9,0x3d7cbddf,0x3d4f3dea,0x3ded3d44,0xbddc3d84,0x3c173dff,0xbdd8bd89,0xbdfb3cc8,0x3d5bbde7,0xbd9dbdca,0x3e00bb49,
0x3dff3c49,0xbdacbdbe,0xbdef3d38,0x3d66bde5,0x3cc8bdfb,0x3d843ddc,0x3dfcbcaf,0xbd9d3dca,0xbd443ded,0xbd2cbdf1,0xbe00bb49,0x3dc2bda7,0x3d8ebdd5,0x3c963dfd,0x3dfa3ce0,0xbddf3d7c,
0x3de23d71,0xbd84bddc,0xbdf73d09,0x3db1bdb9,0x3dd5bd8e,0xbd5b3de7,0x3dc23da7,0xbdfcbcaf,0xbdedbd44,0x3dfdbc96,0x3c7bbdfe,0x3d4f3dea,0x3cc83dfb,0xbdacbdbe,0xbde53d66,0x3d89bdd8,
0x3da23dc6,0xbd2cbdf1,0xbdfc3caf,0x3ddfbd7c,0x3dfb3cc8,0xbdfd3c96,0xbb493e00,0xbd21bdf3,0x3d44bded,0xbbc93e00,0x3dfa3ce0,0xbdfe3c7b,0xbdd5bd8e,0x3df83cf9,0x3d4fbdea,0xbc173dff,
0x3d153df5,0xbc96bdfd,0xbdff3c17,0x3dfabce0,0x3d8e3dd5,0xbdacbdbe,0xbdca3d9d,0x3db1bdb9,0x3ded3d44,0xbdf8bcf9,0xbd213df3,0x3cafbdfc,0x3dfbbcc8,0xbdf13d2c,0x3d093df7,0xbd4fbdea,
0xbc493dff,0x3bc9be00,0xbe00bb49,0x3dff3c17,0xbcc83dfb,0x3cf9bdf8,0xbdfabce0,0x3df73d09,0xbd443ded,0x3d5bbde7,0xbdeabd4f,0x3de53d66,0xbd8e3dd5,0x3d98bdce,0xbdd1bd93,0x3dca3d9d,
0xbd713de2,0x3cf9bdf8,0xbdfebc7b,0x3def3d38,0xbdd53d8e,0x3df1bd2c,0xbd66bde5,0x3ce03dfa,0xbdedbd44,0x3dce3d98,0x3d7cbddf,0xbdb13db9,0xbcc8bdfb,0xbbc93e00,0x3dffbc17,0xbdfcbcaf,
0xbdc63da2,0x3d5bbde7,0xbdfabce0,0x3dca3d9d,0xbdfbbcc8,0x3dce3d98,0x3d4fbdea,0xbdc23da7,0x3d44bded,0xbdbe3dac,0x3dd13d93,0xbd7cbddf,0x3dd53d8e,0xbd84bddc,0xbdb93db1,0x3df3bd21,
0xbdf53d15,0x3d98bdce,0xbdf3bd21,0x3d933dd1,0xbd8ebdd5,0xbbc93e00,0x3df7bd09,0xbdefbd38,0x3ded3d44,0xbd84bddc,0xbda73dc2,0x3dfabce0,0xbdfb3cc8,0x3de73d5b,0x3c7bbdfe,0xbdb13db9,
0xbdffbc49,0x3dbebdac,0xbdeabd4f,0x3d213df3,0x3cc8bdfb,0xbddc3d84,0x3dd13d93,0xbc7bbdfe,0xbd443ded,0x3df1bd2c,0xbdb1bdb9,0xbc173dff,0x3d8ebdd5,0xbdfd3c96,0x3d893dd8,0x3d09bdf7,
0xbde2bd71,0x3ddcbd84,0xbddfbd7c,0x3b493e00,0x3dd5bd8e,0xbde7bd5b,0x3c173dff,0x3dd1bd93,0xbdedbd44,0x3c963dfd,0x3dcabd9d,0xbdefbd38,0x3cc83dfb,0x3dbebdac,0xbdf3bd21,0x3ce03dfa,
0xbda2bdc6,0x3df1bd2c,0xbdd1bd93,0xbd093df7,0x3dfb3cc8,0xbc96bdfd,0xbdb93db1,0x3de53d66,0x3d44bded,0xbe00bbc9,0x3d893dd8,0x3d9dbdca,0xbdd5bd8e,0xbcf93df8,0x3defbd38,0xbda7bdc2,
0xbd15bdf5,0x3dfdbc96,0xbdc2bda7,0xbd893dd8,0x3d8e3dd5,0x3dbebdac,0xbdfebc7b,0x3b493e00,0x3ded3d44,0x3cf9bdf8,0xbde53d66,0x3d933dd1,0x3dfbbcc8,0xbd2cbdf1,0xbd7c3ddf,0x3def3d38,
0x3c49bdff,0x3e003bc9,0xbdb1bdb9,0xbdc23da7,0xbcc83dfb,0x3df83cf9,0xbd89bdd8,0xbddf3d7c,0xbd443ded,0x3de73d5b,0xbd38bdef,0xbdf33d21,0xbd8e3dd5,0x3dce3d98,0xbcafbdfc,0xbdfe3c7b,
0x3d71bde2,0x3df83cf9,0xbd9dbdca,0xbdea3d4f,0xbdd53d8e,0x3d2c3df1,0x3d21bdf3,0xbdd8bd89,0xbdedbd44,0xbd983dce,0x3df7bd09,0xbb49be00,0xbcc8bdfb,0xbe00bbc9,0x3dc23da7,0x3dd1bd93,
0x3dc6bda2,0x3de73d5b,0xbd89bdd8,0xbdfe3c7b,0xbdfbbcc8,0xbd983dce,0x3defbd38,0x3c17bdff,0x3d44bded,0xbdacbdbe,0x3caf3dfc,0x3df73d09,0x3dd53d8e,0x3ddcbd84,0xbe00bb49,0xbd663de5,
0x3df5bd15,0x3dce3d98,0xbd66bde5,0xbdfcbcaf,0xbd8ebdd5,0xbe00bbc9,0x3ddf3d7c,0x3deabd4f,0x3ded3d44,0x3ddcbd84,0xbdff3c17,0xbd893dd8,0xbdfb3cc8,0xbd5b3de7,0x3dcabd9d,0xbb49be00,
0x3dff3c49,0x3dac3dbe,0xbd38bdef,0xbde5bd66,0x3cc8bdfb,0xbd84bddc,0x3caf3dfc,0x3dca3d9d,0xbd443ded,0x3d2c3df1,0x3b49be00,0xbda7bdc2,0x3d8ebdd5,0xbc96bdfd,0xbce03dfa,0x3d7c3ddf,
0x3de23d71,0x3d843ddc,0xbd09bdf7,0xbdb9bdb1,0x3dd5bd8e,0x3d5bbde7,0xbda73dc2,0xbcaf3dfc,0xbdedbd44,0xbdfd3c96,0x3dfe3c7b,0x3deabd4f,0x3cc83dfb,0x3dac3dbe,0xbd66bde5,0xbdd8bd89,
0x3da23dc6,0x3d2c3df1,0xbcafbdfc,0xbd7cbddf,0x3dfb3cc8,0x3dfdbc96,0xbe00bb49,0xbdf33d21,0x3d44bded,0x3bc9be00,0xbce03dfa,0x3c7b3dfe,0xbdd5bd8e,0xbdf8bcf9,0x3dea3d4f,0x3dff3c17,
0x3d153df5,0x3c963dfd,0xbc17bdff,0xbce0bdfa,0x3d8e3dd5,0x3dac3dbe,0xbd9dbdca,0xbdb9bdb1,0x3ded3d44,0x3df83cf9,0xbdf3bd21,0xbdfcbcaf,0x3dfbbcc8,0x3df1bd2c,0xbdf73d09,0xbdea3d4f,
0xbdb53d80,0xbdbe3dac,0xbdb93db1,0xbdc23da7,0xbd153df5,0xbddc3d84,0xbdd83d89,0xbddf3d7c,0xbd713de2,0xbdf13d2c,0xbdef3d38,0xbdf33d21,0xbda23dc6,0xbdfd3c96,0xbdfc3caf,0xbdfe3c7b,
0x3db53d80,0x3ddcbd84,0x3dcabd9d,0x3deabd4f,0xbdff3c49,0x3de73d5b,0x3df33d21,0x3dd83d89,0xbda2bdc6,0x3c963dfd,0x3d093df7,0x3b493e00,0x3d15bdf5,0xbdbe3dac,0xbda73dc2,0xbdd13d93,
0xbdb53d80,0xbdf13d2c,0xbdd83d89,0xbdfe3c7b,0xbd71bde2,0xbc96bdfd,0xbd38bdef,0x3c17bdff,0x3df5bd15,0x3e003bc9,0x3dfcbcaf,0x3df73d09,0x3c493dff,0xbcf93df8,0xbb493e00,0xbd663de5,
0x3db53d80,0x3dfdbc96,0x3de5bd66,0x3dfc3caf,0x3da2bdc6,0xbdbe3dac,0xbd7c3ddf,0xbdea3d4f,0xbc493dff,0x3cf9bdf8,0xbc17bdff,0x3d89bdd8,0xbd71bde2,0x3d2c3df1,0x3d9d3dca,0x3b493e00,
0xbdb53d80,0xbe00bbc9,0xbdef3d38,0xbde5bd66,0x3df53d15,0x3df83cf9,0x3dfcbcaf,0x3dca3d9d,0xbde2bd71,0xbde7bd5b,0xbe00bb49,0xbda7bdc2,0x3dc63da2,0x3dce3d98,0x3dfa3ce0,0x3d7c3ddf,
0x3db53d80,0x3df83cf9,0x3df7bd09,0x3db93db1,0x3c493dff,0xbd2cbdf1,0xbdc2bda7,0x3cafbdfc,0x3dc6bda2,0xbd983dce,0xbc7b3dfe,0xbdea3d4f,0xbdf5bd15,0x3e003bc9,0x3de5bd66,0x3dd83d89,
0xbdb53d80,0xbde7bd5b,0xbdfc3caf,0xbd7cbddf,0xbde23d71,0xbd983dce,0xbb493e00,0xbdf33d21,0x3d153df5,0x3dac3dbe,0x3dfa3ce0,0x3c7b3dfe,0x3dffbc49,0x3ddcbd84,0x3d4fbdea,0x3dff3c17,
0x3db53d80,0x3dce3d98,0x3dffbc17,0x3ce03dfa,0xbdc6bda2,0x3e003bc9,0x3dcabd9d,0x3db93db1,0xbdffbc49,0x3ddcbd84,0x3d21bdf3,0x3dfc3caf,0xbde23d71,0x3d5bbde7,0xbd09bdf7,0x3deabd4f,
0xbdb53d80,0xbdacbdbe,0xbe00bb49,0x3c17bdff,0x3d15bdf5,0xbd84bddc,0xbdfabce0,0x3d09bdf7,0x3d71bde2,0xbd2cbdf1,0xbdeabd4f,0x3d66bde5,0x3da2bdc6,0xbc96bdfd,0xbdd1bd93,0x3d9dbdca,
0x3db53d80,0x3d843ddc,0x3dfe3c7b,0xbd383def,0x3dffbc49,0xbd5b3de7,0x3d663de5,0xbdfa3ce0,0x3da23dc6,0xbdfd3c96,0xbd7c3ddf,0xbdb9bdb1,0xbd153df5,0xbdacbdbe,0xbdff3c17,0x3cafbdfc,
0xbdb53d80,0xbd2cbdf1,0xbdfabce0,0x3d9dbdca,0x3d713de2,0x3dfdbc96,0x3d4fbdea,0x3da73dc2,0xbdf53d15,0xbbc93e00,0x3dd13d93,0xbddf3d7c,0xbc49bdff,0xbdf8bcf9,0xbdb93db1,0xbd21bdf3,
0x3db53d80,0x3c963dfd,0x3df33d21,0xbdd13d93,0xbda23dc6,0xbdacbdbe,0xbdf73d09,0x3d38bdef,0x3c49bdff,0x3df83cf9,0x3da7bdc2,0x3ce03dfa,0x3d713de2,0xbdf13d2c,0xbc7b3dfe,0xbdb9bdb1,
0xbdb53d80,0x3bc9be00,0xbdeabd4f,0x3df3bd21,0xbdf5bd15,0xbcf93df8,0x3dd13d93,0xbdfe3c7b,0x3de23d71,0x3d5bbde7,0xbdb1bdb9,0x3dff3c17,0xbdc6bda2,0xbd983dce,0x3d893dd8,0xbdf7bd09,
0x3db53d80,0xbcf93df8,0x3ddf3d7c,0xbe003b49,0xbc49bdff,0x3df1bd2c,0xbc17bdff,0x3d933dd1,0xbdc63da2,0xbdcebd98,0xbdca3d9d,0x3d38bdef,0x3df53d15,0xbbc93e00,0x3df33d21,0xbdfa3ce0,
0xbdb53d80,0x3d5bbde7,0xbdd1bd93,0x3df73d09,0x3de2bd71,0xbdcebd98,0xbdb93db1,0x3d66bde5,0xbd15bdf5,0xbdbe3dac,0x3d893dd8,0xbdcabd9d,0xbdff3c49,0x3d843ddc,0x3defbd38,0xbdc23da7,
0x3db53d80,0xbd983dce,0x3dc23da7,0xbdd8bd89,0x3dc63da2,0xbbc93e00,0x3dfe3c7b,0xbe003b49,0x3dff3c49,0x3d843ddc,0x3de5bd66,0xbdd13d93,0x3de2bd71,0x3de73d5b,0x3d7cbddf,0xbd383def,
0xbdb53d80,0x3dbebdac,0xbdb1bdb9,0x3da73dc2,0xbd153df5,0x3ddcbd84,0xbd89bdd8,0x3d7c3ddf,0xbd713de2,0x3df1bd2c,0xbd38bdef,0x3d213df3,0xbda23dc6,0x3dfdbc96,0xbcafbdfc,0x3c7b3dfe,
0x3db53d80,0xbddc3d84,0x3d9d3dca,0xbd4fbdea,0xbdff3c49,0xbde7bd5b,0xbd213df3,0x3d89bdd8,0xbda2bdc6,0xbc96bdfd,0xbdf73d09,0x3e00bb49,0x3d15bdf5,0x3dbebdac,0xbdc2bda7,0x3d933dd1,
0xbdb53d80,0x3df1bd2c,0xbd89bdd8,0x3c7b3dfe,0xbd71bde2,0x3c963dfd,0x3defbd38,0xbdffbc17,0x3df5bd15,0xbe00bbc9,0x3caf3dfc,0x3d09bdf7,0x3c493dff,0x3cf9bdf8,0xbe00bb49,0x3de53d66,
0x3db53d80,0xbdfd3c96,0x3d663de5,0x3cafbdfc,0x3da2bdc6,0x3dbebdac,0xbddfbd7c,0x3d4f3dea,0xbc493dff,0xbcf93df8,0x3dffbc17,0xbdd8bd89,0xbd71bde2,0xbd2cbdf1,0xbdca3d9d,0x3e00bb49,
0xbdb53d80,0x3e003bc9,0xbd38bdef,0xbd663de5,0x3df53d15,0xbdf8bcf9,0x3caf3dfc,0x3d9dbdca,0xbde2bd71,0x3de73d5b,0x3b49be00,0xbdc23da7,0x3dc63da2,0xbdcebd98,0xbce03dfa,0x3ddfbd7c,
0x3db53d80,0xbdf8bcf9,0x3d093df7,0x3db1bdb9,0x3c493dff,0x3d2c3df1,0x3da7bdc2,0xbdfcbcaf,0x3dc6bda2,0x3d98bdce,0xbdfebc7b,0x3d4f3dea,0xbdf5bd15,0xbe00bbc9,0x3d663de5,0x3d89bdd8,
0xbdb53d80,0x3de73d5b,0xbcafbdfc,0xbddf3d7c,0xbde23d71,0x3d98bdce,0xbe00bb49,0x3d213df3,0x3d153df5,0xbdacbdbe,0xbce03dfa,0x3dfebc7b,0x3dffbc49,0xbddc3d84,0x3dea3d4f,0x3c17bdff,
0x3db53d80,0xbdcebd98,0x3c173dff,0x3dfabce0,0xbdc6bda2,0xbe00bbc9,0x3d9d3dca,0x3db1bdb9,0xbdffbc49,0xbddc3d84,0x3df33d21,0x3cafbdfc,0xbde23d71,0xbd5b3de7,0x3df7bd09,0xbd4fbdea,
0xbdb53d80,0x3dac3dbe,0x3b49be00,0xbdffbc17,0x3d15bdf5,0x3d843ddc,0x3ce0bdfa,0xbdf7bd09,0x3d71bde2,0x3d2c3df1,0x3d4fbdea,0xbde5bd66,0x3da2bdc6,0x3c963dfd,0x3d93bdd1,0xbdcabd9d,
0x3db53d80,0xbd84bddc,0xbc7b3dfe,0x3def3d38,0x3dffbc49,0x3d5bbde7,0xbde53d66,0x3ce03dfa,0x3da23dc6,0x3dfdbc96,0xbddfbd7c,0xbdb13db9,0xbd153df5,0x3dac3dbe,0xbc17bdff,0xbdfcbcaf,
0xbdb53d80,0x3d2c3df1,0x3ce0bdfa,0xbdcabd9d,0x3d713de2,0xbdfd3c96,0x3dea3d4f,0x3dc2bda7,0xbdf53d15,0x3bc9be00,0xbd933dd1,0x3d7c3ddf,0xbc49bdff,0x3df83cf9,0xbdb1bdb9,0xbdf33d21,
0x3db53d80,0xbc96bdfd,0xbd213df3,0x3d933dd1,0xbda23dc6,0x3dac3dbe,0xbd09bdf7,0xbdefbd38,0x3c49bdff,0xbdf8bcf9,0x3dc23da7,0x3dfabce0,0x3d713de2,0x3df1bd2c,0xbdfebc7b,0xbdb13db9,
0xbdb53d80,0xbbc93e00,0x3d4fbdea,0xbd21bdf3,0xbdf5bd15,0x3cf9bdf8,0xbd933dd1,0x3c7b3dfe,0x3de23d71,0xbd5b3de7,0x3db9bdb1,0x3c17bdff,0xbdc6bda2,0x3d98bdce,0xbdd83d89,0xbd093df7,
0x3db53d80,0x3cf9bdf8,0xbd7c3ddf,0x3b493e00,0xbc49bdff,0xbdf13d2c,0x3dffbc17,0x3dd1bd93,0xbdc63da2,0x3dce3d98,0xbd9dbdca,0xbdefbd38,0x3df53d15,0x3bc9be00,0xbd213df3,0x3ce03dfa,
0xbdb53d80,0xbd5b3de7,0x3d93bdd1,0x3d09bdf7,0x3de2bd71,0x3dce3d98,0xbdb1bdb9,0xbde5bd66,0xbd15bdf5,0x3dbebdac,0xbdd83d89,0xbd9d3dca,0xbdff3c49,0xbd84bddc,0x3d383def,0x3da73dc2,
0x3db53d80,0x3d98bdce,0xbda73dc2,0xbd893dd8,0x3dc63da2,0x3bc9be00,0xbc7b3dfe,0x3b493e00,0x3dff3c49,0xbd84bddc,0x3d663de5,0x3d933dd1,0x3de2bd71,0xbde7bd5b,0x3ddf3d7c,0x3def3d38,
0xbcc83dfb,0xbc493dff,0xbbc93e00,0xbc963dfd,0xbd443ded,0xbd713de2,0xbd5b3de7,0xbd843ddc,0xbdb53db5,0xbdc63da2,0xbdbe3dac,0xbdce3d98,0xbded3d44,0xbdf53d15,0xbdf13d2c,0xbdf83cf9,
0xbd8e3dd5,0xbd153df5,0xbc963dfd,0xbd5b3de7,0xbded3d44,0xbdff3c49,0xbdf83cf9,0xbe00bbc9,0xbdb5bdb5,0xbd71bde2,0xbd98bdce,0xbd2cbdf1,0x3d44bded,0x3da2bdc6,0x3d84bddc,0x3dbebdac,
0xbdd53d8e,0xbd713de2,0xbcf93df8,0xbdac3dbe,0xbdedbd44,0xbda2bdc6,0xbdcebd98,0xbd5bbde7,0x3db5bdb5,0x3df5bd15,0x3ddcbd84,0x3e00bbc9,0x3d443ded,0xbc493dff,0x3c963dfd,0xbd2c3df1,
0xbdfb3cc8,0xbda23dc6,0xbd2c3df1,0xbddc3d84,0xbd44bded,0x3d15bdf5,0xbbc9be00,0x3d98bdce,0x3db53db5,0x3c493dff,0x3d5b3de7,0xbcf93df8,0xbdedbd44,0xbd71bde2,0xbdbebdac,0xbc96bdfd,
0xbdfbbcc8,0xbdc63da2,0xbd5b3de7,0xbdf83cf9,0x3d44bded,0x3df5bd15,0x3dbebdac,0x3dfd3c96,0xbdb53db5,0xbdffbc49,0xbdf13d2c,0xbddcbd84,0x3dedbd44,0x3de23d71,0x3e003bc9,0x3d983dce,
0xbdd5bd8e,0xbde23d71,0xbd843ddc,0xbe00bbc9,0x3dedbd44,0x3dc63da2,0x3dfd3c96,0x3d2c3df1,0xbdb5bdb5,0x3d15bdf5,0xbcf9bdf8,0x3dbebdac,0xbd443ded,0xbdff3c49,0xbdce3d98,0xbde7bd5b,
0xbd8ebdd5,0xbdf53d15,0xbd983dce,0xbdf1bd2c,0x3ded3d44,0xbc493dff,0x3d843ddc,0xbdac3dbe,0x3db5bdb5,0x3de23d71,0x3dfdbc96,0x3d5b3de7,0xbd44bded,0x3dc6bda2,0x3cf9bdf8,0x3e00bbc9,
0xbcc8bdfb,0xbdff3c49,0xbdac3dbe,0xbdcebd98,0x3d443ded,0xbde23d71,0xbd2c3df1,0xbdf8bcf9,0x3db53db5,0xbda23dc6,0x3bc93e00,0xbdfd3c96,0x3ded3d44,0xbd153df5,0x3d5b3de7,0xbddc3d84,
0x3cc8bdfb,0xbdffbc49,0xbdbe3dac,0xbd98bdce,0xbd443ded,0xbde2bd71,0xbdf13d2c,0xbcf9bdf8,0xbdb53db5,0xbda2bdc6,0xbe00bbc9,0x3c96bdfd,0xbded3d44,0xbd15bdf5,0xbde7bd5b,0x3d84bddc,
0x3d8ebdd5,0xbdf5bd15,0xbdce3d98,0xbd2cbdf1,0xbded3d44,0xbc49bdff,0xbddcbd84,0x3dbebdac,0xbdb5bdb5,0x3de2bd71,0x3c96bdfd,0x3de73d5b,0x3d44bded,0x3dc63da2,0x3df8bcf9,0xbbc93e00,
0x3dd5bd8e,0xbde2bd71,0xbddc3d84,0xbbc9be00,0xbdedbd44,0x3dc6bda2,0xbc96bdfd,0x3df13d2c,0x3db5bdb5,0x3d153df5,0x3df83cf9,0xbdac3dbe,0x3d443ded,0xbdffbc49,0xbd983dce,0xbd5bbde7,
0x3dfbbcc8,0xbdc6bda2,0xbde73d5b,0x3cf9bdf8,0xbd44bded,0x3df53d15,0x3dacbdbe,0x3c963dfd,0x3db53db5,0xbdff3c49,0xbd2c3df1,0xbd84bddc,0xbdedbd44,0x3de2bd71,0xbbc9be00,0x3dce3d98,
0x3dfb3cc8,0xbda2bdc6,0xbdf13d2c,0x3d84bddc,0x3d44bded,0x3d153df5,0x3e003bc9,0xbdce3d98,0xbdb53db5,0x3c49bdff,0xbde7bd5b,0x3df8bcf9,0x3dedbd44,0xbd713de2,0x3dac3dbe,0xbdfdbc96,
0x3dd53d8e,0xbd71bde2,0xbdf83cf9,0x3dbebdac,0x3dedbd44,0xbda23dc6,0x3d983dce,0xbde7bd5b,0xbdb5bdb5,0x3df53d15,0x3d84bddc,0xbbc93e00,0xbd443ded,0xbc49bdff,0xbdfdbc96,0x3df1bd2c,
0x3d8e3dd5,0xbd15bdf5,0xbdfd3c96,0x3de7bd5b,0x3ded3d44,0xbdffbc49,0xbcf93df8,0xbbc9be00,0x3db5bdb5,0xbd713de2,0x3dce3d98,0xbdf1bd2c,0xbd44bded,0x3da23dc6,0x3ddcbd84,0xbdac3dbe,
0x3cc83dfb,0xbc49bdff,0xbe003bc9,0x3dfdbc96,0x3d443ded,0xbd71bde2,0xbde73d5b,0x3ddcbd84,0x3db53db5,0xbdc6bda2,0xbdac3dbe,0x3d98bdce,0x3ded3d44,0xbdf5bd15,0xbd2c3df1,0x3cf9bdf8,
0xbcc83dfb,0x3c49bdff,0xbe00bbc9,0x3dfd3c96,0xbd443ded,0x3d71bde2,0xbde7bd5b,0x3ddc3d84,0xbdb53db5,0x3dc6bda2,0xbdacbdbe,0x3d983dce,0xbded3d44,0x3df5bd15,0xbd2cbdf1,0x3cf93df8,
0xbd8e3dd5,0x3d15bdf5,0xbdfdbc96,0x3de73d5b,0xbded3d44,0x3dffbc49,0xbcf9bdf8,0xbbc93e00,0xbdb5bdb5,0x3d713de2,0x3dcebd98,0xbdf13d2c,0x3d44bded,0xbda23dc6,0x3ddc3d84,0xbdacbdbe,
0xbdd53d8e,0x3d71bde2,0xbdf8bcf9,0x3dbe3dac,0xbdedbd44,0x3da23dc6,0x3d98bdce,0xbde73d5b,0x3db5bdb5,0xbdf53d15,0x3d843ddc,0xbbc9be00,0x3d443ded,0x3c49bdff,0xbdfd3c96,0x3df13d2c,
0xbdfb3cc8,0x3da2bdc6,0xbdf1bd2c,0x3d843ddc,0xbd44bded,0xbd153df5,0x3e00bbc9,0xbdcebd98,0x3db53db5,0xbc49bdff,0xbde73d5b,0x3df83cf9,0xbdedbd44,0x3d713de2,0x3dacbdbe,0xbdfd3c96,
0xbdfbbcc8,0x3dc6bda2,0xbde7bd5b,0x3cf93df8,0x3d44bded,0xbdf53d15,0x3dac3dbe,0x3c96bdfd,0xbdb53db5,0x3dff3c49,0xbd2cbdf1,0xbd843ddc,0x3dedbd44,0xbde2bd71,0xbbc93e00,0x3dcebd98,
0xbdd5bd8e,0x3de2bd71,0xbddcbd84,0xbbc93e00,0x3dedbd44,0xbdc6bda2,0xbc963dfd,0x3df1bd2c,0xbdb5bdb5,0xbd153df5,0x3df8bcf9,0xbdacbdbe,0xbd443ded,0x3dffbc49,0xbd98bdce,0xbd5b3de7,
0xbd8ebdd5,0x3df5bd15,0xbdcebd98,0xbd2c3df1,0x3ded3d44,0x3c49bdff,0xbddc3d84,0x3dbe3dac,0x3db5bdb5,0xbde2bd71,0x3c963dfd,0x3de7bd5b,0xbd44bded,0xbdc63da2,0x3df83cf9,0xbbc9be00,
0xbcc8bdfb,0x3dffbc49,0xbdbebdac,0xbd983dce,0x3d443ded,0x3de2bd71,0xbdf1bd2c,0xbcf93df8,0x3db53db5,0x3da2bdc6,0xbe003bc9,0x3c963dfd,0x3ded3d44,0x3d15bdf5,0xbde73d5b,0x3d843ddc,
0x3cc8bdfb,0x3dff3c49,0xbdacbdbe,0xbdce3d98,0xbd443ded,0x3de23d71,0xbd2cbdf1,0xbdf83cf9,0xbdb53db5,0x3da23dc6,0x3bc9be00,0xbdfdbc96,0xbded3d44,0x3d153df5,0x3d5bbde7,0xbddcbd84,
0x3d8ebdd5,0x3df53d15,0xbd98bdce,0xbdf13d2c,0xbded3d44,0x3c493dff,0x3d84bddc,0xbdacbdbe,0xbdb5bdb5,0xbde23d71,0x3dfd3c96,0x3d5bbde7,0x3d44bded,0xbdc6bda2,0x3cf93df8,0x3e003bc9,
0x3dd5bd8e,0x3de23d71,0xbd84bddc,0xbe003bc9,0xbdedbd44,0xbdc63da2,0x3dfdbc96,0x3d2cbdf1,0x3db5bdb5,0xbd15bdf5,0xbcf93df8,0x3dbe3dac,0x3d443ded,0x3dff3c49,0xbdcebd98,0xbde73d5b,
0x3dfbbcc8,0x3dc63da2,0xbd5bbde7,0xbdf8bcf9,0xbd44bded,0xbdf5bd15,0x3dbe3dac,0x3dfdbc96,0x3db53db5,0x3dffbc49,0xbdf1bd2c,0xbddc3d84,0xbdedbd44,0xbde23d71,0x3e00bbc9,0x3d98bdce,
0x3dfb3cc8,0x3da23dc6,0xbd2cbdf1,0xbddcbd84,0x3d44bded,0xbd15bdf5,0xbbc93e00,0x3d983dce,0xbdb53db5,0xbc493dff,0x3d5bbde7,0xbcf9bdf8,0x3dedbd44,0x3d71bde2,0xbdbe3dac,0xbc963dfd,
0x3dd53d8e,0x3d713de2,0xbcf9bdf8,0xbdacbdbe,0x3dedbd44,0x3da2bdc6,0xbdce3d98,0xbd5b3de7,0xbdb5bdb5,0xbdf5bd15,0x3ddc3d84,0x3e003bc9,0xbd443ded,0x3c493dff,0x3c96bdfd,0xbd2cbdf1,
0x3d8e3dd5,0x3d153df5,0xbc96bdfd,0xbd5bbde7,0x3ded3d44,0x3dff3c49,0xbdf8bcf9,0xbe003bc9,0x3db5bdb5,0x3d71bde2,0xbd983dce,0xbd2c3df1,0xbd44bded,0xbda2bdc6,0x3d843ddc,0x3dbe3dac,
0x3cc83dfb,0x3c493dff,0xbbc9be00,0xbc96bdfd,0x3d443ded,0x3d713de2,0xbd5bbde7,0xbd84bddc,0x3db53db5,0x3dc63da2,0xbdbebdac,0xbdcebd98,0x3ded3d44,0x3df53d15,0xbdf1bd2c,0xbdf8bcf9,
0xbd803d80,0xbdffbc49,0xbe00bbc9,0xbdfdbc96,0xbd8e3dd5,0xbde2bd71,0xbde7bd5b,0xbddcbd84,0xbdd53d8e,0xbda2bdc6,0xbdacbdbe,0xbd98bdce,0xbdfb3cc8,0xbd15bdf5,0xbd2cbdf1,0xbcf9bdf8,
0x3d803d80,0x3df53d15,0x3dfd3c96,0x3de73d5b,0xbdfbbcc8,0x3c493dff,0x3cf93df8,0xbbc93e00,0xbcc8bdfb,0xbde23d71,0xbdce3d98,0xbdf13d2c,0x3dd5bd8e,0xbdc6bda2,0xbddcbd84,0xbdacbdbe,
0xbd803d80,0xbde2bd71,0xbdf8bcf9,0xbdbebdac,0xbcc8bdfb,0x3dc6bda2,0x3d98bdce,0x3de7bd5b,0x3dfb3cc8,0x3d153df5,0x3d843ddc,0x3bc93e00,0xbd8e3dd5,0xbdffbc49,0xbdfd3c96,0xbdf1bd2c,
0x3d803d80,0x3dc63da2,0x3df13d2c,0x3d843ddc,0x3dd5bd8e,0xbdf5bd15,0xbe003bc9,0xbdcebd98,0xbd8e3dd5,0x3dffbc49,0x3de7bd5b,0x3df83cf9,0x3cc8bdfb,0xbde23d71,0xbdac3dbe,0xbdfd3c96,
0xbd803d80,0xbda2bdc6,0xbde7bd5b,0xbcf9bdf8,0x3dd53d8e,0x3d153df5,0x3dac3dbe,0xbc963dfd,0xbd8ebdd5,0x3c49bdff,0xbd2cbdf1,0x3d84bddc,0x3cc83dfb,0xbd713de2,0xbbc93e00,0xbdce3d98,
0x3d803d80,0x3d713de2,0x3ddc3d84,0xbbc93e00,0xbcc83dfb,0x3da2bdc6,0x3c96bdfd,0x3df1bd2c,0x3dfbbcc8,0xbdf5bd15,0xbdf83cf9,0xbdacbdbe,0xbd8ebdd5,0x3c493dff,0x3d983dce,0xbd5b3de7,
0xbd803d80,0xbd15bdf5,0xbdcebd98,0x3d2cbdf1,0xbdfb3cc8,0xbdffbc49,0xbddc3d84,0xbdbebdac,0xbcc83dfb,0xbd713de2,0x3c963dfd,0xbde73d5b,0x3dd53d8e,0x3da23dc6,0x3df83cf9,0x3bc93e00,
0x3d803d80,0x3c493dff,0x3dbe3dac,0xbd983dce,0xbd8ebdd5,0x3d713de2,0x3df13d2c,0xbcf93df8,0xbdd5bd8e,0x3dc63da2,0x3e00bbc9,0x3c963dfd,0xbdfbbcc8,0x3df53d15,0x3de7bd5b,0x3d843ddc,
0xbd803d80,0x3c49bdff,0xbdacbdbe,0x3dcebd98,0x3d8ebdd5,0x3d71bde2,0xbd2cbdf1,0x3df8bcf9,0x3dd5bd8e,0x3dc6bda2,0x3bc9be00,0x3dfd3c96,0x3dfbbcc8,0x3df5bd15,0x3d5bbde7,0x3ddc3d84,
0x3d803d80,0xbd153df5,0x3d983dce,0xbdf13d2c,0x3dfb3cc8,0xbdff3c49,0xbd843ddc,0xbdacbdbe,0x3cc83dfb,0xbd71bde2,0xbdfdbc96,0x3d5bbde7,0xbdd53d8e,0x3da2bdc6,0xbcf9bdf8,0x3e003bc9,
0xbd803d80,0x3d71bde2,0xbd84bddc,0x3e00bbc9,0x3cc83dfb,0x3da23dc6,0x3dfdbc96,0xbd2c3df1,0xbdfbbcc8,0xbdf53d15,0xbcf93df8,0xbdbebdac,0x3d8ebdd5,0x3c49bdff,0xbdcebd98,0x3de7bd5b,
0x3d803d80,0xbda23dc6,0x3d5b3de7,0xbdf8bcf9,0xbdd53d8e,0x3d15bdf5,0xbdbebdac,0x3dfdbc96,0x3d8ebdd5,0x3c493dff,0x3df13d2c,0xbddc3d84,0xbcc83dfb,0xbd71bde2,0xbe003bc9,0x3d98bdce,
0xbd803d80,0x3dc6bda2,0xbd2cbdf1,0x3ddc3d84,0xbdd5bd8e,0xbdf53d15,0xbbc93e00,0xbd98bdce,0x3d8e3dd5,0x3dff3c49,0x3d5bbde7,0x3cf93df8,0xbcc8bdfb,0xbde2bd71,0xbdbe3dac,0x3c96bdfd,
0x3d803d80,0xbde23d71,0x3cf93df8,0xbdacbdbe,0x3cc8bdfb,0x3dc63da2,0x3dcebd98,0xbd5b3de7,0xbdfb3cc8,0x3d15bdf5,0xbddcbd84,0x3e003bc9,0x3d8e3dd5,0xbdff3c49,0xbc963dfd,0xbd2cbdf1,
0xbd803d80,0x3df5bd15,0xbc96bdfd,0x3d5b3de7,0x3dfbbcc8,0x3c49bdff,0xbdf8bcf9,0x3e00bbc9,0x3cc8bdfb,0xbde2bd71,0xbd983dce,0x3d2cbdf1,0xbdd5bd8e,0xbdc63da2,0x3d843ddc,0xbdbebdac,
0x3d803d80,0xbdff3c49,0x3bc93e00,0xbc96bdfd,0x3d8e3dd5,0xbde23d71,0x3d5b3de7,0xbd84bddc,0x3dd53d8e,0xbda23dc6,0x3dbe3dac,0xbdcebd98,0x3dfb3cc8,0xbd153df5,0x3df13d2c,0xbdf8bcf9,
0xbd803d80,0x3dff3c49,0x3bc9be00,0xbc963dfd,0xbd8e3dd5,0x3de23d71,0x3d5bbde7,0xbd843ddc,0xbdd53d8e,0x3da23dc6,0x3dbebdac,0xbdce3d98,0xbdfb3cc8,0x3d153df5,0x3df1bd2c,0xbdf83cf9,
0x3d803d80,0xbdf5bd15,0xbc963dfd,0x3d5bbde7,0xbdfbbcc8,0xbc49bdff,0xbdf83cf9,0x3e003bc9,0xbcc8bdfb,0x3de2bd71,0xbd98bdce,0x3d2c3df1,0x3dd5bd8e,0x3dc63da2,0x3d84bddc,0xbdbe3dac,
0xbd803d80,0x3de23d71,0x3cf9bdf8,0xbdac3dbe,0xbcc8bdfb,0xbdc63da2,0x3dce3d98,0xbd5bbde7,0x3dfb3cc8,0xbd15bdf5,0xbddc3d84,0x3e00bbc9,0xbd8e3dd5,0x3dff3c49,0xbc96bdfd,0xbd2c3df1,
0x3d803d80,0xbdc6bda2,0xbd2c3df1,0x3ddcbd84,0x3dd5bd8e,0x3df53d15,0xbbc9be00,0xbd983dce,0xbd8e3dd5,0xbdff3c49,0x3d5b3de7,0x3cf9bdf8,0x3cc8bdfb,0x3de2bd71,0xbdbebdac,0x3c963dfd,
0xbd803d80,0x3da23dc6,0x3d5bbde7,0xbdf83cf9,0x3dd53d8e,0xbd15bdf5,0xbdbe3dac,0x3dfd3c96,0xbd8ebdd5,0xbc493dff,0x3df1bd2c,0xbddcbd84,0x3cc83dfb,0x3d71bde2,0xbe00bbc9,0x3d983dce,
0x3d803d80,0xbd71bde2,0xbd843ddc,0x3e003bc9,0xbcc83dfb,0xbda23dc6,0x3dfd3c96,0xbd2cbdf1,0x3dfbbcc8,0x3df53d15,0xbcf9bdf8,0xbdbe3dac,0xbd8ebdd5,0xbc49bdff,0xbdce3d98,0x3de73d5b,
0xbd803d80,0x3d153df5,0x3d98bdce,0xbdf1bd2c,0xbdfb3cc8,0x3dff3c49,0xbd84bddc,0xbdac3dbe,0xbcc83dfb,0x3d71bde2,0xbdfd3c96,0x3d5b3de7,0x3dd53d8e,0xbda2bdc6,0xbcf93df8,0x3e00bbc9,
0x3d803d80,0xbc49bdff,0xbdac3dbe,0x3dce3d98,0xbd8ebdd5,0xbd71bde2,0xbd2c3df1,0x3df83cf9,0xbdd5bd8e,0xbdc6bda2,0x3bc93e00,0x3dfdbc96,0xbdfbbcc8,0xbdf5bd15,0x3d5b3de7,0x3ddcbd84,
0xbd803d80,0xbc493dff,0x3dbebdac,0xbd98bdce,0x3d8ebdd5,0xbd713de2,0x3df1bd2c,0xbcf9bdf8,0x3dd5bd8e,0xbdc63da2,0x3e003bc9,0x3c96bdfd,0x3dfbbcc8,0xbdf53d15,0x3de73d5b,0x3d84bddc,
0x3d803d80,0x3d15bdf5,0xbdce3d98,0x3d2c3df1,0x3dfb3cc8,0x3dffbc49,0xbddcbd84,0xbdbe3dac,0x3cc83dfb,0x3d713de2,0x3c96bdfd,0xbde7bd5b,0xbdd53d8e,0xbda23dc6,0x3df8bcf9,0x3bc9be00,
0xbd803d80,0xbd713de2,0x3ddcbd84,0xbbc9be00,0x3cc83dfb,0xbda2bdc6,0x3c963dfd,0x3df13d2c,0xbdfbbcc8,0x3df5bd15,0xbdf8bcf9,0xbdac3dbe,0x3d8ebdd5,0xbc493dff,0x3d98bdce,0xbd5bbde7,
0x3d803d80,0x3da2bdc6,0xbde73d5b,0xbcf93df8,0xbdd53d8e,0xbd153df5,0x3dacbdbe,0xbc96bdfd,0x3d8ebdd5,0xbc49bdff,0xbd2c3df1,0x3d843ddc,0xbcc83dfb,0x3d713de2,0xbbc9be00,0xbdcebd98,
0xbd803d80,0xbdc63da2,0x3df1bd2c,0x3d84bddc,0xbdd5bd8e,0x3df5bd15,0xbe00bbc9,0xbdce3d98,0x3d8e3dd5,0xbdffbc49,0x3de73d5b,0x3df8bcf9,0xbcc8bdfb,0x3de23d71,0xbdacbdbe,0xbdfdbc96,
0x3d803d80,0x3de2bd71,0xbdf83cf9,0xbdbe3dac,0x3cc8bdfb,0xbdc6bda2,0x3d983dce,0x3de73d5b,0xbdfb3cc8,0xbd153df5,0x3d84bddc,0x3bc9be00,0x3d8e3dd5,0x3dffbc49,0xbdfdbc96,0xbdf13d2c,
0xbd803d80,0xbdf53d15,0x3dfdbc96,0x3de7bd5b,0x3dfbbcc8,0xbc493dff,0x3cf9bdf8,0xbbc9be00,0x3cc8bdfb,0x3de23d71,0xbdcebd98,0xbdf1bd2c,0xbdd5bd8e,0x3dc6bda2,0xbddc3d84,0xbdac3dbe,
0x3d803d80,0x3dffbc49,0xbe003bc9,0xbdfd3c96,0x3d8e3dd5,0x3de2bd71,0xbde73d5b,0xbddc3d84,0x3dd53d8e,0x3da2bdc6,0xbdac3dbe,0xbd983dce,0x3dfb3cc8,0x3d15bdf5,0xbd2c3df1,0xbcf93df8,
0xbd153df5,0xbc963dfd,0xbc173dff,0xbce03dfa,0xbd8e3dd5,0xbdac3dbe,0xbd9d3dca,0xbdb93db1,0xbded3d44,0xbdf83cf9,0xbdf33d21,0xbdfc3caf,0xbdfbbcc8,0xbdf1bd2c,0xbdf7bd09,0xbdeabd4f,
0xbda23dc6,0xbd2c3df1,0xbcaf3dfc,0xbd7c3ddf,0xbdfb3cc8,0xbdfdbc96,0xbe003b49,0xbdf3bd21,0xbd44bded,0xbbc9be00,0xbce0bdfa,0x3c7bbdfe,0x3dd5bd8e,0x3df8bcf9,0x3deabd4f,0x3dffbc17,
0xbde23d71,0xbd843ddc,0xbd093df7,0xbdb93db1,0xbdd5bd8e,0xbd5bbde7,0xbda7bdc2,0xbcafbdfc,0x3dedbd44,0x3dfd3c96,0x3dfebc7b,0x3dea3d4f,0xbcc83dfb,0xbdac3dbe,0xbd663de5,0xbdd83d89,
0xbdff3c49,0xbdac3dbe,0xbd383def,0xbde53d66,0xbcc8bdfb,0x3d84bddc,0x3cafbdfc,0x3dcabd9d,0x3d443ded,0xbd2c3df1,0x3b493e00,0xbda73dc2,0xbd8ebdd5,0x3c96bdfd,0xbce0bdfa,0x3d7cbddf,
0xbdf5bd15,0xbdce3d98,0xbd663de5,0xbdfc3caf,0x3d8ebdd5,0x3e00bbc9,0x3ddfbd7c,0x3dea3d4f,0xbded3d44,0xbddcbd84,0xbdffbc17,0xbd89bdd8,0x3dfb3cc8,0x3d5b3de7,0x3dca3d9d,0xbb493e00,
0xbdc6bda2,0xbde73d5b,0xbd893dd8,0xbdfebc7b,0x3dfbbcc8,0x3d983dce,0x3def3d38,0x3c173dff,0xbd44bded,0x3dacbdbe,0x3cafbdfc,0x3df7bd09,0xbdd53d8e,0xbddcbd84,0xbe003b49,0xbd66bde5,
0xbd71bde2,0xbdf83cf9,0xbd9d3dca,0xbdeabd4f,0x3dd53d8e,0xbd2c3df1,0x3d213df3,0xbdd83d89,0x3dedbd44,0x3d983dce,0x3df73d09,0xbb493e00,0x3cc8bdfb,0x3e00bbc9,0x3dc2bda7,0x3dd13d93,
0xbc49bdff,0xbe003bc9,0xbdb13db9,0xbdc2bda7,0x3cc83dfb,0xbdf83cf9,0xbd893dd8,0xbddfbd7c,0x3d443ded,0xbde73d5b,0xbd383def,0xbdf3bd21,0x3d8e3dd5,0xbdce3d98,0xbcaf3dfc,0xbdfebc7b,
0x3d15bdf5,0xbdfdbc96,0xbdc23da7,0xbd89bdd8,0xbd8e3dd5,0xbdbebdac,0xbdfe3c7b,0x3b49be00,0xbded3d44,0xbcf9bdf8,0xbde5bd66,0x3d93bdd1,0xbdfbbcc8,0x3d2cbdf1,0xbd7cbddf,0x3defbd38,
0x3da2bdc6,0xbdf1bd2c,0xbdd13d93,0xbd09bdf7,0xbdfb3cc8,0x3c96bdfd,0xbdb9bdb1,0x3de5bd66,0xbd44bded,0x3e00bbc9,0x3d89bdd8,0x3d9d3dca,0x3dd5bd8e,0x3cf93df8,0x3def3d38,0xbda73dc2,
0x3de2bd71,0xbddcbd84,0xbddf3d7c,0x3b49be00,0xbdd5bd8e,0x3de7bd5b,0x3c17bdff,0x3dd13d93,0x3dedbd44,0xbc963dfd,0x3dca3d9d,0xbdef3d38,0xbcc83dfb,0xbdbebdac,0xbdf33d21,0x3ce0bdfa,
0x3dffbc49,0xbdbebdac,0xbdea3d4f,0x3d21bdf3,0xbcc8bdfb,0x3ddc3d84,0x3dd1bd93,0xbc7b3dfe,0x3d443ded,0xbdf1bd2c,0xbdb13db9,0xbc17bdff,0xbd8ebdd5,0x3dfd3c96,0x3d89bdd8,0x3d093df7,
0x3df53d15,0xbd98bdce,0xbdf33d21,0x3d93bdd1,0x3d8ebdd5,0x3bc93e00,0x3df73d09,0xbdef3d38,0xbded3d44,0x3d84bddc,0xbda7bdc2,0x3dfa3ce0,0x3dfb3cc8,0xbde73d5b,0x3c7b3dfe,0xbdb1bdb9,
0x3dc63da2,0xbd5bbde7,0xbdfa3ce0,0x3dcabd9d,0x3dfbbcc8,0xbdce3d98,0x3d4f3dea,0xbdc2bda7,0xbd44bded,0x3dbe3dac,0x3dd1bd93,0xbd7c3ddf,0xbdd53d8e,0x3d84bddc,0xbdb9bdb1,0x3df33d21,
0x3d713de2,0xbcf9bdf8,0xbdfe3c7b,0x3defbd38,0x3dd53d8e,0xbdf1bd2c,0xbd663de5,0x3ce0bdfa,0x3dedbd44,0xbdce3d98,0x3d7c3ddf,0xbdb1bdb9,0x3cc8bdfb,0x3bc93e00,0x3dff3c17,0xbdfc3caf,
0x3c493dff,0xbbc9be00,0xbe003b49,0x3dffbc17,0x3cc83dfb,0xbcf9bdf8,0xbdfa3ce0,0x3df7bd09,0x3d443ded,0xbd5bbde7,0xbdea3d4f,0x3de5bd66,0x3d8e3dd5,0xbd98bdce,0xbdd13d93,0x3dcabd9d,
0xbd153df5,0x3c96bdfd,0xbdffbc17,0x3dfa3ce0,0xbd8e3dd5,0x3dacbdbe,0xbdcabd9d,0x3db13db9,0xbded3d44,0x3df8bcf9,0xbd21bdf3,0x3caf3dfc,0xbdfbbcc8,0x3df13d2c,0x3d09bdf7,0xbd4f3dea,
0xbda23dc6,0x3d2cbdf1,0xbdfcbcaf,0x3ddf3d7c,0xbdfb3cc8,0x3dfd3c96,0xbb49be00,0xbd213df3,0xbd44bded,0x3bc93e00,0x3dfabce0,0xbdfebc7b,0x3dd5bd8e,0xbdf83cf9,0x3d4f3dea,0xbc17bdff,
0xbde23d71,0x3d84bddc,0xbdf7bd09,0x3db13db9,0xbdd5bd8e,0x3d5b3de7,0x3dc2bda7,0xbdfc3caf,0x3dedbd44,0xbdfdbc96,0x3c7b3dfe,0x3d4fbdea,0xbcc83dfb,0x3dacbdbe,0xbde5bd66,0x3d893dd8,
0xbdff3c49,0x3dacbdbe,0xbdefbd38,0x3d663de5,0xbcc8bdfb,0xbd843ddc,0x3dfc3caf,0xbd9dbdca,0x3d443ded,0x3d2cbdf1,0xbe003b49,0x3dc23da7,0xbd8ebdd5,0xbc963dfd,0x3dfabce0,0xbddfbd7c,
0xbdf5bd15,0x3dcebd98,0xbde5bd66,0x3caf3dfc,0x3d8ebdd5,0xbe003bc9,0x3d7c3ddf,0x3d4fbdea,0xbded3d44,0x3ddc3d84,0x3c17bdff,0xbdd83d89,0x3dfb3cc8,0xbd5bbde7,0xbd9d3dca,0x3e003b49,
0xbdc6bda2,0x3de7bd5b,0xbdd8bd89,0xbc7b3dfe,0x3dfbbcc8,0xbd98bdce,0xbd383def,0x3dffbc17,0xbd44bded,0xbdac3dbe,0x3dfc3caf,0xbd09bdf7,0xbdd53d8e,0x3ddc3d84,0xbb49be00,0xbde53d66,
0xbd71bde2,0x3df8bcf9,0xbdcabd9d,0xbd4f3dea,0x3dd53d8e,0x3d2cbdf1,0xbdf33d21,0x3d893dd8,0x3dedbd44,0xbd98bdce,0xbd093df7,0x3e003b49,0x3cc8bdfb,0xbe003bc9,0x3da73dc2,0x3d93bdd1,
0xbc49bdff,0x3e00bbc9,0xbdb9bdb1,0xbda73dc2,0x3cc83dfb,0x3df8bcf9,0xbdd8bd89,0xbd7c3ddf,0x3d443ded,0x3de7bd5b,0xbdefbd38,0xbd213df3,0x3d8e3dd5,0x3dcebd98,0xbdfcbcaf,0xbc7b3dfe,
0x3d15bdf5,0x3dfd3c96,0xbda7bdc2,0xbdd83d89,0xbd8e3dd5,0x3dbe3dac,0xbc7bbdfe,0xbe00bb49,0xbded3d44,0x3cf93df8,0x3d66bde5,0xbdd1bd93,0xbdfbbcc8,0xbd2c3df1,0x3ddfbd7c,0xbd38bdef,
0x3da2bdc6,0x3df13d2c,0xbd93bdd1,0xbdf73d09,0xbdfb3cc8,0xbc963dfd,0x3db1bdb9,0xbd66bde5,0xbd44bded,0xbe003bc9,0x3dd83d89,0x3dcabd9d,0x3dd5bd8e,0xbcf9bdf8,0xbd383def,0x3dc23da7,
0x3de2bd71,0x3ddc3d84,0xbd7cbddf,0xbe00bb49,0xbdd5bd8e,0xbde73d5b,0x3dff3c17,0x3d93bdd1,0x3dedbd44,0x3c96bdfd,0xbd9d3dca,0x3d383def,0xbcc83dfb,0x3dbe3dac,0xbd21bdf3,0xbdfabce0,
0x3dffbc49,0x3dbe3dac,0xbd4fbdea,0xbdf3bd21,0xbcc8bdfb,0xbddcbd84,0x3d933dd1,0x3dfe3c7b,0x3d443ded,0x3df13d2c,0xbdb9bdb1,0xbdff3c17,0xbd8ebdd5,0xbdfdbc96,0x3dd83d89,0x3df7bd09,
0x3df53d15,0x3d983dce,0xbd21bdf3,0xbdd1bd93,0x3d8ebdd5,0xbbc9be00,0xbd093df7,0x3d383def,0xbded3d44,0xbd843ddc,0x3dc2bda7,0x3ce0bdfa,0x3dfb3cc8,0x3de7bd5b,0xbdfe3c7b,0xbdb93db1,
0x3dc63da2,0x3d5b3de7,0xbce0bdfa,0xbd9dbdca,0x3dfbbcc8,0x3dcebd98,0xbdea3d4f,0xbda73dc2,0xbd44bded,0xbdbebdac,0x3d933dd1,0x3ddf3d7c,0xbdd53d8e,0xbd843ddc,0x3db1bdb9,0x3d21bdf3,
0x3d713de2,0x3cf93df8,0xbc7bbdfe,0xbd38bdef,0x3dd53d8e,0x3df13d2c,0xbde5bd66,0xbdfabce0,0x3dedbd44,0x3dcebd98,0xbddf3d7c,0xbdb93db1,0x3cc8bdfb,0xbbc9be00,0xbc173dff,0x3caf3dfc,
0x3c493dff,0x3bc93e00,0xbb49be00,0xbc17bdff,0x3cc83dfb,0x3cf93df8,0xbce0bdfa,0xbd09bdf7,0x3d443ded,0x3d5b3de7,0xbd4fbdea,0xbd66bde5,0x3d8e3dd5,0x3d983dce,0xbd93bdd1,0xbd9dbdca,
0xbdb53d80,0xbd98bdce,0xbda7bdc2,0xbd89bdd8,0xbdc63da2,0xbbc9be00,0xbc7bbdfe,0x3b49be00,0xbdff3c49,0x3d84bddc,0x3d66bde5,0x3d93bdd1,0xbde2bd71,0x3de7bd5b,0x3ddfbd7c,0x3defbd38,
0x3db53d80,0x3d5b3de7,0x3d933dd1,0x3d093df7,0xbde2bd71,0xbdce3d98,0xbdb13db9,0xbde53d66,0x3d15bdf5,0xbdbebdac,0xbdd8bd89,0xbd9dbdca,0x3dff3c49,0x3d84bddc,0x3d38bdef,0x3da7bdc2,
0xbdb53d80,0xbcf9bdf8,0xbd7cbddf,0x3b49be00,0x3c49bdff,0x3df13d2c,0x3dff3c17,0x3dd13d93,0x3dc63da2,0xbdce3d98,0xbd9d3dca,0xbdef3d38,0xbdf53d15,0xbbc9be00,0xbd21bdf3,0x3ce0bdfa,
0x3db53d80,0x3bc93e00,0x3d4f3dea,0xbd213df3,0x3df5bd15,0xbcf9bdf8,0xbd93bdd1,0x3c7bbdfe,0xbde23d71,0x3d5b3de7,0x3db93db1,0x3c173dff,0x3dc6bda2,0xbd98bdce,0xbdd8bd89,0xbd09bdf7,
0xbdb53d80,0x3c96bdfd,0xbd21bdf3,0x3d93bdd1,0x3da23dc6,0xbdac3dbe,0xbd093df7,0xbdef3d38,0xbc49bdff,0x3df8bcf9,0x3dc2bda7,0x3dfa3ce0,0xbd713de2,0xbdf1bd2c,0xbdfe3c7b,0xbdb1bdb9,
0x3db53d80,0xbd2c3df1,0x3ce03dfa,0xbdca3d9d,0xbd713de2,0x3dfd3c96,0x3deabd4f,0x3dc23da7,0x3df53d15,0xbbc9be00,0xbd93bdd1,0x3d7cbddf,0x3c49bdff,0xbdf83cf9,0xbdb13db9,0xbdf3bd21,
0xbdb53d80,0x3d84bddc,0xbc7bbdfe,0x3defbd38,0xbdffbc49,0xbd5bbde7,0xbde5bd66,0x3ce0bdfa,0xbda23dc6,0xbdfdbc96,0xbddf3d7c,0xbdb1bdb9,0x3d153df5,0xbdac3dbe,0xbc173dff,0xbdfc3caf,
0x3db53d80,0xbdac3dbe,0x3b493e00,0xbdff3c17,0xbd15bdf5,0xbd843ddc,0x3ce03dfa,0xbdf73d09,0xbd71bde2,0xbd2c3df1,0x3d4f3dea,0xbde53d66,0xbda2bdc6,0xbc963dfd,0x3d933dd1,0xbdca3d9d,
0xbdb53d80,0x3dcebd98,0x3c17bdff,0x3dfa3ce0,0x3dc6bda2,0x3e00bbc9,0x3d9dbdca,0x3db13db9,0x3dffbc49,0x3ddc3d84,0x3df3bd21,0x3caf3dfc,0x3de23d71,0x3d5b3de7,0x3df73d09,0xbd4f3dea,
0x3db53d80,0xbde73d5b,0xbcaf3dfc,0xbddfbd7c,0x3de23d71,0xbd98bdce,0xbe003b49,0x3d21bdf3,0xbd153df5,0x3dacbdbe,0xbce0bdfa,0x3dfe3c7b,0xbdffbc49,0x3ddc3d84,0x3deabd4f,0x3c173dff,
0xbdb53d80,0x3df8bcf9,0x3d09bdf7,0x3db13db9,0xbc493dff,0xbd2c3df1,0x3da73dc2,0xbdfc3caf,0xbdc6bda2,0xbd98bdce,0xbdfe3c7b,0x3d4fbdea,0x3df5bd15,0x3e00bbc9,0x3d66bde5,0x3d893dd8,
0x3db53d80,0xbe003bc9,0xbd383def,0xbd66bde5,0xbdf53d15,0x3df8bcf9,0x3cafbdfc,0x3d9d3dca,0x3de2bd71,0xbde73d5b,0x3b493e00,0xbdc2bda7,0xbdc63da2,0x3dcebd98,0xbce0bdfa,0x3ddf3d7c,
0xbdb53d80,0x3dfd3c96,0x3d66bde5,0x3caf3dfc,0xbda2bdc6,0xbdbebdac,0xbddf3d7c,0x3d4fbdea,0x3c493dff,0x3cf93df8,0x3dff3c17,0xbdd83d89,0x3d71bde2,0x3d2cbdf1,0xbdcabd9d,0x3e003b49,
0x3db53d80,0xbdf1bd2c,0xbd893dd8,0x3c7bbdfe,0x3d71bde2,0xbc963dfd,0x3def3d38,0xbdff3c17,0xbdf5bd15,0x3e00bbc9,0x3cafbdfc,0x3d093df7,0xbc493dff,0xbcf9bdf8,0xbe003b49,0x3de5bd66,
0xbdb53d80,0x3ddc3d84,0x3d9dbdca,0xbd4f3dea,0x3dff3c49,0x3de7bd5b,0xbd21bdf3,0x3d893dd8,0x3da2bdc6,0x3c96bdfd,0xbdf7bd09,0x3e003b49,0xbd15bdf5,0xbdbebdac,0xbdc23da7,0x3d93bdd1,
0x3db53d80,0xbdbebdac,0xbdb13db9,0x3da7bdc2,0x3d153df5,0xbddcbd84,0xbd893dd8,0x3d7cbddf,0x3d713de2,0xbdf1bd2c,0xbd383def,0x3d21bdf3,0x3da23dc6,0xbdfdbc96,0xbcaf3dfc,0x3c7bbdfe,
0xbdb53d80,0x3d983dce,0x3dc2bda7,0xbdd83d89,0xbdc63da2,0x3bc93e00,0x3dfebc7b,0xbe00bb49,0xbdff3c49,0xbd843ddc,0x3de53d66,0xbdd1bd93,0xbde2bd71,0xbde73d5b,0x3d7c3ddf,0xbd38bdef,
0x3db53d80,0xbd5bbde7,0xbdd13d93,0x3df7bd09,0xbde2bd71,0x3dcebd98,0xbdb9bdb1,0x3d663de5,0x3d15bdf5,0x3dbe3dac,0x3d89bdd8,0xbdca3d9d,0x3dff3c49,0xbd843ddc,0x3def3d38,0xbdc2bda7,
0xbdb53d80,0x3cf93df8,0x3ddfbd7c,0xbe00bb49,0x3c49bdff,0xbdf1bd2c,0xbc173dff,0x3d93bdd1,0x3dc63da2,0x3dcebd98,0xbdcabd9d,0x3d383def,0xbdf53d15,0x3bc93e00,0x3df3bd21,0xbdfabce0,
0x3db53d80,0xbbc9be00,0xbdea3d4f,0x3df33d21,0x3df5bd15,0x3cf93df8,0x3dd1bd93,0xbdfebc7b,0xbde23d71,0xbd5bbde7,0xbdb13db9,0x3dffbc17,0x3dc6bda2,0x3d983dce,0x3d89bdd8,0xbdf73d09,
0xbdb53d80,0xbc963dfd,0x3df3bd21,0xbdd1bd93,0x3da23dc6,0x3dacbdbe,0xbdf7bd09,0x3d383def,0xbc49bdff,0xbdf83cf9,0x3da73dc2,0x3ce0bdfa,0xbd713de2,0x3df13d2c,0xbc7bbdfe,0xbdb93db1,
0x3db53d80,0x3d2cbdf1,0xbdfa3ce0,0x3d9d3dca,0xbd713de2,0xbdfdbc96,0x3d4f3dea,0x3da7bdc2,0x3df53d15,0x3bc93e00,0x3dd1bd93,0xbddfbd7c,0x3c49bdff,0x3df8bcf9,0xbdb9bdb1,0xbd213df3,
0xbdb53d80,0xbd843ddc,0x3dfebc7b,0xbd38bdef,0xbdffbc49,0x3d5b3de7,0x3d66bde5,0xbdfabce0,0xbda23dc6,0x3dfd3c96,0xbd7cbddf,0xbdb93db1,0x3d153df5,0x3dacbdbe,0xbdffbc17,0x3caf3dfc,
0x3db53d80,0x3dacbdbe,0xbe003b49,0x3c173dff,0xbd15bdf5,0x3d84bddc,0xbdfa3ce0,0x3d093df7,0xbd71bde2,0x3d2cbdf1,0xbdea3d4f,0x3d663de5,0xbda2bdc6,0x3c96bdfd,0xbdd13d93,0x3d9d3dca,
0xbdb53d80,0xbdce3d98,0x3dff3c17,0x3ce0bdfa,0x3dc6bda2,0xbe003bc9,0x3dca3d9d,0x3db9bdb1,0x3dffbc49,0xbddcbd84,0x3d213df3,0x3dfcbcaf,0x3de23d71,0xbd5bbde7,0xbd093df7,0x3dea3d4f,
0x3db53d80,0x3de7bd5b,0xbdfcbcaf,0xbd7c3ddf,0x3de23d71,0x3d983dce,0xbb49be00,0xbdf3bd21,0xbd153df5,0xbdac3dbe,0x3dfabce0,0x3c7bbdfe,0xbdffbc49,0xbddcbd84,0x3d4f3dea,0x3dffbc17,
0xbdb53d80,0xbdf83cf9,0x3df73d09,0x3db9bdb1,0xbc493dff,0x3d2cbdf1,0xbdc23da7,0x3caf3dfc,0xbdc6bda2,0x3d983dce,0xbc7bbdfe,0xbdeabd4f,0x3df5bd15,0xbe003bc9,0x3de53d66,0x3dd8bd89,
0x3db53d80,0x3e00bbc9,0xbdefbd38,0xbde53d66,0xbdf53d15,0xbdf83cf9,0x3dfc3caf,0x3dcabd9d,0x3de2bd71,0x3de7bd5b,0xbe003b49,0xbda73dc2,0xbdc63da2,0xbdce3d98,0x3dfabce0,0x3d7cbddf,
0xbdb53d80,0xbdfdbc96,0x3de53d66,0x3dfcbcaf,0xbda2bdc6,0x3dbe3dac,0xbd7cbddf,0xbdeabd4f,0x3c493dff,0xbcf9bdf8,0xbc173dff,0x3d893dd8,0x3d71bde2,0xbd2c3df1,0x3d9dbdca,0x3b49be00,
0x3db53d80,0x3df13d2c,0xbdd8bd89,0xbdfebc7b,0x3d71bde2,0x3c96bdfd,0xbd383def,0x3c173dff,0xbdf5bd15,0xbe003bc9,0x3dfc3caf,0x3df7bd09,0xbc493dff,0x3cf93df8,0xbb49be00,0xbd66bde5,
0xbdb53d80,0xbddcbd84,0x3dca3d9d,0x3dea3d4f,0x3dff3c49,0xbde73d5b,0x3df3bd21,0x3dd8bd89,0x3da2bdc6,0xbc963dfd,0x3d09bdf7,0x3b49be00,0xbd15bdf5,0x3dbe3dac,0xbda7bdc2,0xbdd1bd93,
0x3db53d80,0x3dbe3dac,0xbdb9bdb1,0xbdc2bda7,0x3d153df5,0x3ddc3d84,0xbdd8bd89,0xbddfbd7c,0x3d713de2,0x3df13d2c,0xbdefbd38,0xbdf3bd21,0x3da23dc6,0x3dfd3c96,0xbdfcbcaf,0xbdfebc7b,
0x3f800000,0x0,0x3f800000,0x0,0x3f800000,0x0,0x3f800000,0x0,0x3f800000,0x0,0x3f800000,0x0,0x3f800000,0x0,0x3f800000,0x0,
0x3f800000,0x0,0x3f7ffb11,0xbc490e90,0x3f7fec43,0xbcc90ab0,0x3f7fd397,0xbd16c32c,0x3f7fb10f,0xbd48fb30,0x3f7f84ab,0xbd7b2b74,0x3f7f4e6d,0xbd96a905,0x3f7f0e58,0xbdafb680,
0x3f800000,0x0,0x3f7fec43,0xbcc90ab0,0x3f7fb10f,0xbd48fb30,0x3f7f4e6d,0xbd96a905,0x3f7ec46d,0xbdc8bd36,0x3f7e1324,0xbdfab273,0x3f7d3aac,0xbe164083,0x3f7c3b28,0xbe2f10a2,
0x3f800000,0x0,0x3f7fd397,0xbd16c32c,0x3f7f4e6d,0xbd96a905,0x3f7e70b0,0xbde1bc2e,0x3f7d3aac,0xbe164083,0x3f7baccd,0xbe3b6ecf,0x3f79c79d,0xbe605c13,0x3f778bc5,0xbe827dc0,
0x3f800000,0x0,0x3f7fb10f,0xbd48fb30,0x3f7ec46d,0xbdc8bd36,0x3f7d3aac,0xbe164083,0x3f7b14be,0xbe47c5c2,0x3f7853f8,0xbe78cfcc,0x3f74fa0b,0xbe94a031,0x3f710908,0xbeac7cd4,
0x3f800000,0x0,0x3f7f84ab,0xbd7b2b74,0x3f7e1324,0xbdfab273,0x3f7baccd,0xbe3b6ecf,0x3f7853f8,0xbe78cfcc,0x3f740bdd,0xbe9aa086,0x3f6ed89e,0xbeb8442a,0x3f68bf3c,0xbed53641,
0x3f800000,0x0,0x3f7f4e6d,0xbd96a905,0x3f7d3aac,0xbe164083,0x3f79c79d,0xbe605c13,0x3f74fa0b,0xbe94a031,0x3f6ed89e,0xbeb8442a,0x3f676bd8,0xbedae880,0x3f5ebe05,0xbefc5d27,
0x3f800000,0x0,0x3f7f0e58,0xbdafb680,0x3f7c3b28,0xbe2f10a2,0x3f778bc5,0xbe827dc0,0x3f710908,0xbeac7cd4,0x3f68bf3c,0xbed53641,0x3f5ebe05,0xbefc5d27,0x3f531849,0xbf10d3cd,
0x3f800000,0x0,0x3f7b14be,0xbe47c5c2,0x3f6c835e,0xbec3ef15,0x3f54db31,0xbf0e39da,0x3f3504f3,0xbf3504f3,0x3f0e39da,0xbf54db31,0x3ec3ef15,0xbf6c835e,0x3e47c5c2,0xbf7b14be,
0x3f800000,0x0,0x3f7a7302,0xbe541501,0x3f6a09a7,0xbecf7bca,0x3f4f7a1f,0xbf15f6d9,0x3f2beb4a,0xbf3daef9,0x3f00e7e4,0xbf5d2d53,0x3ea09ae5,0xbf731447,0x3de1bc2e,0xbf7e70b0,
0x3f800000,0x0,0x3f79c79d,0xbe605c13,0x3f676bd8,0xbedae880,0x3f49d112,0xbf1d7fd1,0x3f226799,0xbf45e403,0x3ee63375,0xbf64aa59,0x3e78cfcc,0xbf7853f8,0x3cc90ab0,0xbf7fec43,
0x3f800000,0x0,0x3f791298,0xbe6c9a7f,0x3f64aa59,0xbee63375,0x3f43e200,0xbf24d225,0x3f187fc0,0xbf4d9f02,0x3ec9b953,0xbf6b4b0c,0x3e2f10a2,0xbf7c3b28,0xbd7b2b74,0xbf7f84ab,
0x3f800000,0x0,0x3f7853f8,0xbe78cfcc,0x3f61c598,0xbef15aea,0x3f3daef9,0xbf2beb4a,0x3f0e39da,0xbf54db31,0x3eac7cd4,0xbf710908,0x3dc8bd36,0xbf7ec46d,0xbe164083,0xbf7d3aac,
0x3f800000,0x0,0x3f778bc5,0xbe827dc0,0x3f5ebe05,0xbefc5d27,0x3f373a23,0xbf32c8c9,0x3f039c3d,0xbf5b941a,0x3e8e9a22,0xbf75dec6,0x3cc90ab0,0xbf7fec43,0xbe6c9a7f,0xbf791298,
0x3f800000,0x0,0x3f76ba07,0xbe888e93,0x3f5b941a,0xbf039c3d,0x3f3085bb,0xbf396842,0x3ef15aea,0xbf61c598,0x3e605c13,0xbf79c79d,0xbd48fb30,0xbf7fb10f,0xbea09ae5,0xbf731447,
0x3f800000,0x0,0x3f75dec6,0xbe8e9a22,0x3f584853,0xbf08f59b,0x3f299415,0xbf3fc767,0x3edae880,0xbf676bd8,0x3e22abb6,0xbf7cbfc9,0xbdfab273,0xbf7e1324,0xbec9b953,0xbf6b4b0c,
0x3f800000,0x0,0x3f7ec46d,0xbdc8bd36,0x3f7b14be,0xbe47c5c2,0x3f74fa0b,0xbe94a031,0x3f6c835e,0xbec3ef15,0x3f61c598,0xbef15aea,0x3f54db31,0xbf0e39da,0x3f45e403,0xbf226799,
0x3f800000,0x0,0x3f6b4b0c,0xbec9b953,0x3f3085bb,0xbf396842,0x3eb263ef,0xbf6ff573,0xbd48fb30,0xbf7fb10f,0xbee0924f,0xbf660f88,0xbf41d870,0xbf273656,0xbf740bdd,0xbe9aa086,
0x3f800000,0x0,0x3f6a09a7,0xbecf7bca,0x3f2beb4a,0xbf3daef9,0x3ea09ae5,0xbf731447,0xbdc8bd36,0xbf7ec46d,0xbefc5d27,0xbf5ebe05,0xbf4d9f02,0xbf187fc0,0xbf79c79d,0xbe605c13,
0x3f800000,0x0,0x3f68bf3c,0xbed53641,0x3f273656,0xbf41d870,0x3e8e9a22,0xbf75dec6,0xbe164083,0xbf7d3aac,0xbf0b9a6b,0xbf5695e5,0xbf584853,0xbf08f59b,0xbf7dabcc,0xbe09cf86,
0x3f800000,0x0,0x3f676bd8,0xbedae880,0x3f226799,0xbf45e403,0x3e78cfcc,0xbf7853f8,0xbe47c5c2,0xbf7b14be,0xbf187fc0,0xbf4d9f02,0xbf61c598,0xbef15aea,0xbf7fb10f,0xbd48fb30,
0x3f800000,0x0,0x3f660f88,0xbee0924f,0x3f1d7fd1,0xbf49d112,0x3e541501,0xbf7a7302,0xbe78cfcc,0xbf7853f8,0xbf24d225,0xbf43e200,0xbf6a09a7,0xbecf7bca,0xbf7fd397,0x3d16c32c,
0x3f800000,0x0,0x3f64aa59,0xbee63375,0x3f187fc0,0xbf4d9f02,0x3e2f10a2,0xbf7c3b28,0xbe94a031,0xbf74fa0b,0xbf3085bb,0xbf396842,0xbf710908,0xbeac7cd4,0xbf7e1324,0x3dfab273,
0x3f800000,0x0,0x3f633c5a,0xbeebcbbb,0x3f13682a,0xbf514d3d,0x3e09cf86,0xbf7dabcc,0xbeac7cd4,0xbf710908,0xbf3b8f3b,0xbf2e3bde,0xbf76ba07,0xbe888e93,0xbf7a7302,0x3e541501,
0x3f800000,0x0,0x3f74fa0b,0xbe94a031,0x3f54db31,0xbf0e39da,0x3f226799,0xbf45e403,0x3ec3ef15,0xbf6c835e,0x3dc8bd36,0xbf7ec46d,0xbe47c5c2,0xbf7b14be,0xbef15aea,0xbf61c598,
0x3f800000,0x0,0x3f531849,0xbf10d3cd,0x3eb8442a,0xbf6ed89e,0xbe6c9a7f,0xbf791298,0xbf3daef9,0xbf2beb4a,0xbf7dabcc,0xbe09cf86,0xbf64aa59,0x3ee63375,0xbef6e0cb,0x3f604621,
0x3f800000,0x0,0x3f514d3d,0xbf13682a,0x3eac7cd4,0xbf710908,0xbe888e93,0xbf76ba07,0xbf45e403,0xbf226799,0xbf7f4e6d,0xbd96a905,0xbf5b941a,0x3f039c3d,0xbecf7bca,0x3f6a09a7,
0x3f800000,0x0,0x3f4f7a1f,0xbf15f6d9,0x3ea09ae5,0xbf731447,0xbe9aa086,0xbf740bdd,0xbf4d9f02,0xbf187fc0,0xbf7ffb11,0xbc490e90,0xbf514d3d,0x3f13682a,0xbea68f12,0x3f721352,
0x3f800000,0x0,0x3f4d9f02,0xbf187fc0,0x3e94a031,0xbf74fa0b,0xbeac7cd4,0xbf710908,0xbf54db31,0xbf0e39da,0xbf7fb10f,0x3d48fb30,0xbf45e403,0x3f226799,0xbe78cfcc,0x3f7853f8,
0x3f800000,0x0,0x3f4bbbf8,0xbf1b02c6,0x3e888e93,0xbf76ba07,0xbebe1d4a,0xbf6db293,0xbf5b941a,0xbf039c3d,0xbf7e70b0,0x3de1bc2e,0xbf396842,0x3f3085bb,0xbe22abb6,0x3f7cbfc9,
0x3f800000,0x0,0x3f49d112,0xbf1d7fd1,0x3e78cfcc,0xbf7853f8,0xbecf7bca,0xbf6a09a7,0xbf61c598,0xbef15aea,0xbf7c3b28,0x3e2f10a2,0xbf2beb4a,0x3f3daef9,0xbd96a905,0x3f7f4e6d,
0x3f800000,0x0,0x3f47de65,0xbf1ff6cb,0x3e605c13,0xbf79c79d,0xbee0924f,0xbf660f88,0xbf676bd8,0xbedae880,0xbf791298,0x3e6c9a7f,0xbf1d7fd1,0x3f49d112,0x3c490e90,0x3f7ffb11,
0x3f800000,0x0,0x3f800000,0x0,0x3f800000,0x0,0x3f800000,0x0,0x40000000,0x0,0x3f800000,0x0,0x3f800000,0x0,0x3f800000,0x0,
0x3f800000,0x0,0x3f7ffb11,0xbc490e90,0x3f7fec43,0xbcc90ab0,0x3f7fd397,0xbd16c32c,0x3fffb10f,0xbdc8fb30,0x3f7f84ab,0xbd7b2b74,0x3f7f4e6d,0xbd96a905,0x3f7f0e58,0xbdafb680,
0x3f800000,0x0,0x3f7fec43,0xbcc90ab0,0x3f7fb10f,0xbd48fb30,0x3f7f4e6d,0xbd96a905,0x3ffec46d,0xbe48bd36,0x3f7e1324,0xbdfab273,0x3f7d3aac,0xbe164083,0x3f7c3b28,0xbe2f10a2,
0x3f800000,0x0,0x3f7fd397,0xbd16c32c,0x3f7f4e6d,0xbd96a905,0x3f7e70b0,0xbde1bc2e,0x3ffd3aac,0xbe964083,0x3f7baccd,0xbe3b6ecf,0x3f79c79d,0xbe605c13,0x3f778bc5,0xbe827dc0,
0x3f800000,0x0,0x3f7fb10f,0xbd48fb30,0x3f7ec46d,0xbdc8bd36,0x3f7d3aac,0xbe164083,0x3ffb14be,0xbec7c5c2,0x3f7853f8,0xbe78cfcc,0x3f74fa0b,0xbe94a031,0x3f710908,0xbeac7cd4,
0x3f800000,0x0,0x3f7f84ab,0xbd7b2b74,0x3f7e1324,0xbdfab273,0x3f7baccd,0xbe3b6ecf,0x3ff853f8,0xbef8cfcc,0x3f740bdd,0xbe9aa086,0x3f6ed89e,0xbeb8442a,0x3f68bf3c,0xbed53641,
0x3f800000,0x0,0x3f7f4e6d,0xbd96a905,0x3f7d3aac,0xbe164083,0x3f79c79d,0xbe605c13,0x3ff4fa0b,0xbf14a031,0x3f6ed89e,0xbeb8442a,0x3f676bd8,0xbedae880,0x3f5ebe05,0xbefc5d27,
0x3f800000,0x0,0x3f7f0e58,0xbdafb680,0x3f7c3b28,0xbe2f10a2,0x3f778bc5,0xbe827dc0,0x3ff10908,0xbf2c7cd4,0x3f68bf3c,0xbed53641,0x3f5ebe05,0xbefc5d27,0x3f531849,0xbf10d3cd,
0x3f800000,0x0,0x3f7ec46d,0xbdc8bd36,0x3f7b14be,0xbe47c5c2,0x3f74fa0b,0xbe94a031,0x3fec835e,0xbf43ef15,0x3f61c598,0xbef15aea,0x3f54db31,0xbf0e39da,0x3f45e403,0xbf226799,
0x3f800000,0x0,0x3f7e70b0,0xbde1bc2e,0x3f79c79d,0xbe605c13,0x3f721352,0xbea68f12,0x3fe76bd8,0xbf5ae880,0x3f59f26a,0xbf064b82,0x3f49d112,0xbf1d7fd1,0x3f373a23,0xbf32c8c9,
0x3f800000,0x0,0x3f7e1324,0xbdfab273,0x3f7853f8,0xbe78cfcc,0x3f6ed89e,0xbeb8442a,0x3fe1c598,0xbf715aea,0x3f514d3d,0xbf13682a,0x3f3daef9,0xbf2beb4a,0x3f273656,0xbf41d870,
0x3f800000,0x0,0x3f7dabcc,0xbe09cf86,0x3f76ba07,0xbe888e93,0x3f6b4b0c,0xbec9b953,0x3fdb941a,0xbf839c3d,0x3f47de65,0xbf1ff6cb,0x3f3085bb,0xbf396842,0x3f15f6d9,0xbf4f7a1f,
0x3f800000,0x0,0x3f7d3aac,0xbe164083,0x3f74fa0b,0xbe94a031,0x3f676bd8,0xbedae880,0x3fd4db31,0xbf8e39da,0x3f3daef9,0xbf2beb4a,0x3f226799,0xbf45e403,0x3f039c3d,0xbf5b941a,
0x3f800000,0x0,0x3f7cbfc9,0xbe22abb6,0x3f731447,0xbea09ae5,0x3f633c5a,0xbeebcbbb,0x3fcd9f02,0xbf987fc0,0x3f32c8c9,0xbf373a23,0x3f13682a,0xbf514d3d,0x3ee0924f,0xbf660f88,
0x3f800000,0x0,0x3f7c3b28,0xbe2f10a2,0x3f710908,0xbeac7cd4,0x3f5ebe05,0xbefc5d27,0x3fc5e403,0xbfa26799,0x3f273656,0xbf41d870,0x3f039c3d,0xbf5b941a,0x3eb8442a,0xbf6ed89e,
0x3f800000,0x0,0x3f7baccd,0xbe3b6ecf,0x3f6ed89e,0xbeb8442a,0x3f59f26a,0xbf064b82,0x3fbdaef9,0xbfabeb4a,0x3f1b02c6,0xbf4bbbf8,0x3ee63375,0xbf64aa59,0x3e8e9a22,0xbf75dec6,
0x3f800000,0x0,0x3f7b14be,0xbe47c5c2,0x3f6c835e,0xbec3ef15,0x3f54db31,0xbf0e39da,0x3fb504f3,0xbfb504f3,0x3f0e39da,0xbf54db31,0x3ec3ef15,0xbf6c835e,0x3e47c5c2,0xbf7b14be,
0x3f800000,0x0,0x3f7a7302,0xbe541501,0x3f6a09a7,0xbecf7bca,0x3f4f7a1f,0xbf15f6d9,0x3fabeb4a,0xbfbdaef9,0x3f00e7e4,0xbf5d2d53,0x3ea09ae5,0xbf731447,0x3de1bc2e,0xbf7e70b0,
0x3f800000,0x0,0x3f79c79d,0xbe605c13,0x3f676bd8,0xbedae880,0x3f49d112,0xbf1d7fd1,0x3fa26799,0xbfc5e403,0x3ee63375,0xbf64aa59,0x3e78cfcc,0xbf7853f8,0x3cc90ab0,0xbf7fec43,
0x3f800000,0x0,0x3f791298,0xbe6c9a7f,0x3f64aa59,0xbee63375,0x3f43e200,0xbf24d225,0x3f987fc0,0xbfcd9f02,0x3ec9b953,0xbf6b4b0c,0x3e2f10a2,0xbf7c3b28,0xbd7b2b74,0xbf7f84ab,
0x3f800000,0x0,0x3f7853f8,0xbe78cfcc,0x3f61c598,0xbef15aea,0x3f3daef9,0xbf2beb4a,0x3f8e39da,0xbfd4db31,0x3eac7cd4,0xbf710908,0x3dc8bd36,0xbf7ec46d,0xbe164083,0xbf7d3aac,
0x3f800000,0x0,0x3f778bc5,0xbe827dc0,0x3f5ebe05,0xbefc5d27,0x3f373a23,0xbf32c8c9,0x3f839c3d,0xbfdb941a,0x3e8e9a22,0xbf75dec6,0x3cc90ab0,0xbf7fec43,0xbe6c9a7f,0xbf791298,
0x3f800000,0x0,0x3f76ba07,0xbe888e93,0x3f5b941a,0xbf039c3d,0x3f3085bb,0xbf396842,0x3f715aea,0xbfe1c598,0x3e605c13,0xbf79c79d,0xbd48fb30,0xbf7fb10f,0xbea09ae5,0xbf731447,
0x3f800000,0x0,0x3f75dec6,0xbe8e9a22,0x3f584853,0xbf08f59b,0x3f299415,0xbf3fc767,0x3f5ae880,0xbfe76bd8,0x3e22abb6,0xbf7cbfc9,0xbdfab273,0xbf7e1324,0xbec9b953,0xbf6b4b0c,
0x3f800000,0x0,0x3f74fa0b,0xbe94a031,0x3f54db31,0xbf0e39da,0x3f226799,0xbf45e403,0x3f43ef15,0xbfec835e,0x3dc8bd36,0xbf7ec46d,0xbe47c5c2,0xbf7b14be,0xbef15aea,0xbf61c598,
0x3f800000,0x0,0x3f740bdd,0xbe9aa086,0x3f514d3d,0xbf13682a,0x3f1b02c6,0xbf4bbbf8,0x3f2c7cd4,0xbff10908,0x3d16c32c,0xbf7fd397,0xbe888e93,0xbf76ba07,0xbf0b9a6b,0xbf5695e5,
0x3f800000,0x0,0x3f731447,0xbea09ae5,0x3f4d9f02,0xbf187fc0,0x3f13682a,0xbf514d3d,0x3f14a031,0xbff4fa0b,0xbcc90ab0,0xbf7fec43,0xbeac7cd4,0xbf710908,0xbf1d7fd1,0xbf49d112,
0x3f800000,0x0,0x3f721352,0xbea68f12,0x3f49d112,0xbf1d7fd1,0x3f0b9a6b,0xbf5695e5,0x3ef8cfcc,0xbff853f8,0xbdafb680,0xbf7f0e58,0xbecf7bca,0xbf6a09a7,0xbf2e3bde,0xbf3b8f3b,
0x3f800000,0x0,0x3f710908,0xbeac7cd4,0x3f45e403,0xbf226799,0x3f039c3d,0xbf5b941a,0x3ec7c5c2,0xbffb14be,0xbe164083,0xbf7d3aac,0xbef15aea,0xbf61c598,0xbf3daef9,0xbf2beb4a,
0x3f800000,0x0,0x3f6ff573,0xbeb263ef,0x3f41d870,0xbf273656,0x3ef6e0cb,0xbf604621,0x3e964083,0xbffd3aac,0xbe541501,0xbf7a7302,0xbf08f59b,0xbf584853,0xbf4bbbf8,0xbf1b02c6,
0x3f800000,0x0,0x3f6ed89e,0xbeb8442a,0x3f3daef9,0xbf2beb4a,0x3ee63375,0xbf64aa59,0x3e48bd36,0xbffec46d,0xbe888e93,0xbf76ba07,0xbf187fc0,0xbf4d9f02,0xbf584853,0xbf08f59b,
0x3f800000,0x0,0x3f6db293,0xbebe1d4a,0x3f396842,0xbf3085bb,0x3ed53641,0xbf68bf3c,0x3dc8fb30,0xbfffb10f,0xbea68f12,0xbf721352,0xbf273656,0xbf41d870,0xbf633c5a,0xbeebcbbb,
0x3f800000,0x0,0x3f7fffb1,0xbb490fc6,0x3f7ffec4,0xbbc90f88,0x3f7ffd39,0xbc16cb58,0x3ffffb11,0xbcc90e90,0x3f7ff84a,0xbc7b514b,0x3f7ff4e6,0xbc96c9b6,0x3f7ff0e3,0xbcafea69,
0x3f800000,0x0,0x3f7ff84a,0xbc7b514b,0x3f7fe129,0xbcfb49ba,0x3f7fba9e,0xbd3c6dd5,0x3fff84ab,0xbdfb2b74,0x3f7f3f54,0xbd9cecf9,0x3f7eea9d,0xbdbc3ac3,0x3f7e868b,0xbddb7d37,
0x3f800000,0x0,0x3f7fe705,0xbce22a7a,0x3f7f9c18,0xbd621469,0x3f7f1f49,0xbda973ba,0x3ffe70b0,0xbe61bc2e,0x3f7d906e,0xbe0cec4a,0x3f7c7eb0,0xbe28defc,0x3f7b3bab,0xbe44b0b9,
0x3f800000,0x0,0x3f7fcbe2,0xbd2351cb,0x3f7f2f9d,0xbda3308c,0x3f7e2b72,0xbdf475c0,0x3ffcbfc9,0xbea2abb6,0x3f7aed37,0xbe4ada4f,0x3f78b47b,0xbe72b651,0x3f76167a,0xbe8d17c0,
0x3f800000,0x0,0x3f7fa6e3,0xbd55880e,0x3f7e9bc9,0xbdd53db9,0x3f7cdf6c,0xbe1f917b,0x3ffa7302,0xbed41501,0x3f77583a,0xbe840270,0x3f73913f,0xbe9d9e78,0x3f6f20b0,0xbeb6ccc3,
0x3f800000,0x0,0x3f7f7808,0xbd83db0a,0x3f7de0b1,0xbe039502,0x3f7b3bab,0xbe44b0b9,0x3ff78bc5,0xbf027dc0,0x3f72d4eb,0xbea21887,0x3f6d1c1d,0xbec1071e,0x3f666771,0xbedf28a9,
0x3f800000,0x0,0x3f7f3f54,0xbd9cecf9,0x3f7cfe73,0xbe1c76de,0x3f7940c0,0xbe698bba,0x3ff40bdd,0xbf1aa086,0x3f6d67a1,0xbebf926f,0x3f655e0b,0xbee363fa,0x3f5bfb34,0xbf02ef9f,
0x3f800000,0x0,0x3f7efcc9,0xbdb5f8da,0x3f7bf531,0xbe354098,0x3f76ef5b,0xbe870ada,0x3feff573,0xbf3263ef,0x3f671599,0xbedc53c1,0x3f5c61c7,0xbf0242b1,0x3f4fefa8,0xbf1553b7,
0x3f800000,0x0,0x3f7eb069,0xbdcefdb7,0x3f7ac516,0xbe4dee60,0x3f74484b,0xbe9920fe,0x3feb4b0c,0xbf49b953,0x3f5fe4e9,0xbef840c8,0x3f5233c6,0xbf121eb0,0x3f425b89,0xbf269de3,
0x3f800000,0x0,0x3f7e5a38,0xbde7fa9a,0x3f796e4e,0xbe667c66,0x3f714c7a,0xbeab0201,0x3fe60f88,0xbf60924f,0x3f57dc7f,0xbf099f4e,0x3f46e22a,0xbf212ff9,0x3f33587a,0xbf36ad7f,
0x3f800000,0x0,0x3f7dfa38,0xbe007745,0x3f77f110,0xbe7ee6e1,0x3f6dfcf2,0xbebca7af,0x3fe04621,0xbf76e0cb,0x3f4f0417,0xbf16999f,0x3f3a7ca4,0xbf2f61a5,0x3f2302d3,0xbf456439,
0x3f800000,0x0,0x3f7d906e,0xbe0cec4a,0x3f764d97,0xbe8b9507,0x3f6a5ad9,0xbece0bea,0x3fd9f26a,0xbf864b82,0x3f456439,0xbf2302d3,0x3f2d1469,0xbf3ca003,0x3f11796b,0xbf52a649,
0x3f800000,0x0,0x3f7d1cdd,0xbe195be0,0x3f748422,0xbe97a117,0x3f666771,0xbedf28a9,0x3fd31849,0xbf90d3cd,0x3f3b0629,0xbf2ecef7,0x3f1ebc12,0xbf48d8b3,0x3efdbabb,0xbf5e5aa6,
0x3f800000,0x0,0x3f7c9f8a,0xbe25c58c,0x3f7294f8,0xbea395c5,0x3f62241a,0xbeeff7fb,0x3fcbbbf8,0xbf9b02c6,0x3f2ff3e6,0xbf39f2ac,0x3f0f8784,0xbf53fac3,0x3ed6a399,0xbf686b39,
0x3f800000,0x0,0x3f7c187a,0xbe3228d4,0x3f708066,0xbeaf713a,0x3f5d924d,0xbf003a06,0x3fc3e200,0xbfa4d225,0x3f24381a,0xbf446337,0x3eff17b2,0xbf5df6be,0x3eadf73c,0xbf70c501,
0x3f800000,0x0,0x3f7b87b2,0xbe3e853e,0x3f6e46be,0xbebb31a0,0x3f58b3a1,0xbf084b92,0x3fbb8f3b,0xbfae3bde,0x3f17de12,0xbf4e1689,0x3eddbe79,0xbf66becc,0x3e840270,0xbf77583a,
0x3f800000,0x0,0x3f7aed37,0xbe4ada4f,0x3f6be858,0xbec6d529,0x3f5389c7,0xbf102dd5,0x3fb2c8c9,0xbfb73a23,0x3f0af1b7,0xbf570348,0x3ebb31a0,0xbf6e46be,0x3e3228d4,0xbf7c187a,
0x3f800000,0x0,0x3f7a4910,0xbe57278f,0x3f696591,0xbed25a09,0x3f4e1689,0xbf17de12,0x3fa99415,0xbfbfc767,0x3efafef7,0xbf5f20db,0x3e97a117,0xbf748422,0x3db5f8da,0xbf7efcc9,
0x3f800000,0x0,0x3f799b43,0xbe636c83,0x3f66becc,0xbeddbe79,0x3f485bca,0xbf1f599f,0x3f9ff6cb,0xbfc7de65,0x3edf28a9,0xbf666771,0x3e667c66,0xbf796e4e,0x3b490fc6,0xbf7fffb1,
0x3f800000,0x0,0x3f78e3d6,0xbe6fa8b2,0x3f63f473,0xbee900b7,0x3f425b89,0xbf269de3,0x3f95f6d9,0xbfcf7a1f,0x3ec27b55,0xbf6cd007,0x3e1c76de,0xbf7cfe73,0xbda973ba,0xbf7f1f49,
0x3f800000,0x0,0x3f7822d1,0xbe7bdba4,0x3f6106f2,0xbef41f07,0x3f3c17d9,0xbf2da859,0x3f8b9a6b,0xbfd695e5,0x3ea5129f,0xbf725470,0x3da3308c,0xbf7f2f9d,0xbe2bf804,0xbf7c5d3a,
0x3f800000,0x0,0x3f77583a,0xbe840270,0x3f5df6be,0xbeff17b2,0x3f3592e7,0xbf34768f,0x3f80e7e4,0xbfdd2d53,0x3e870ada,0xbf76ef5b,0x3bc90f88,0xbf7ffec4,0xbe80f8c0,0xbf77beb7,
0x3f800000,0x0,0x3f76841b,0xbe8a11f7,0x3f5ac450,0xbf04f484,0x3f2ecef7,0xbf3b0629,0x3f6bcbbb,0xbfe33c5a,0x3e5101f1,0xbf7a9c59,0xbd8a200a,0xbf7f6ac7,0xbeab0201,0xbf714c7a,
0x3f800000,0x0,0x3f75a67b,0xbe901c2c,0x3f577026,0xbf0a48ad,0x3f27ce61,0xbf4154e1,0x3f553641,0xbfe8bf3c,0x3e1324ca,0xbf7d57de,0xbe1008b7,0xbf7d7474,0xbed3c867,0xbf6912ae,
0x3f800000,0x0,0x3f74bf62,0xbe9620d2,0x3f53fac3,0xbf0f8784,0x3f209393,0xbf476085,0x3f3e1d4a,0xbfedb293,0x3da973ba,0xbf7f1f49,0xbe5a3997,0xbf7a1e84,0xbefafef7,0xbf5f20db,
0x3f800000,0x0,0x3f73ced9,0xbe9c1faf,0x3f5064af,0xbf14b039,0x3f19210f,0xbf4d26fd,0x3f268f12,0xbff21352,0x3cafea69,0xbf7ff0e3,0xbe919ddd,0xbf756d97,0xbf102dd5,0xbf5389c7,
0x3f800000,0x0,0x3f72d4eb,0xbea21887,0x3f4cae79,0xbf19c200,0x3f11796b,0xbf52a649,0x3f0e9a22,0xbff5dec6,0xbd2351cb,0xbf7fcbe2,0xbeb554ec,0xbf6f6830,0xbf21cbfb,0xbf466354,
0x3f800000,0x0,0x3f71d19f,0xbea80b1f,0x3f48d8b3,0xbf1ebc12,0x3f099f4e,0xbf57dc7f,0x3eec9a7f,0xbff91298,0xbdcefdb7,0xbf7eb069,0xbed8106b,0xbf6816a8,0xbf3238aa,0xbf37c655,
0x3f800000,0x0,0x3f70c501,0xbeadf73c,0x3f44e3f5,0xbf239da9,0x3f019573,0xbf5cc7d1,0x3ebb6ecf,0xbffbaccd,0xbe25c58c,0xbf7c9f8a,0xbef9a02d,0xbf5f8327,0xbf4154e1,0xbf27ce61,
0x3f800000,0x0,0x3f6faf1b,0xbeb3dca5,0x3f40d0da,0xbf286605,0x3ef2bd43,0xbf61668a,0x3e89cf86,0xbffdabcc,0xbe636c83,0xbf799b43,0xbf0cead0,0xbf55b993,0xbf4f0417,0xbf16999f,
0x3f800000,0x0,0x3f6e8ff8,0xbeb9bb1e,0x3f3ca003,0xbf2d1469,0x3ee1fb6a,0xbf65b710,0x3e2fb680,0xbfff0e58,0xbe901c2c,0xbf75a67b,0xbf1c420c,0xbf4ac77f,0xbf5b2c79,0xbf044889,
0x3f800000,0x0,0x3f6d67a1,0xbebf926f,0x3f385216,0xbf31a81d,0x3ed0eb2a,0xbf69b7e4,0x3d96c32c,0xbfffd397,0xbeadf73c,0xbf70c501,0xbf2ac082,0xbf3ebc1b,0xbf65b710,0xbee1fb6a,
0x3f800000,0x0,0x3f7ffec4,0xbbc90f88,0x3f7ffb11,0xbc490e90,0x3f7ff4e6,0xbc96c9b6,0x3fffec43,0xbd490ab0,0x3f7fe129,0xbcfb49ba,0x3f7fd397,0xbd16c32c,0x3f7fc38f,0xbd2fe007,
0x3f800000,0x0,0x3f7ff4e6,0xbc96c9b6,0x3f7fd397,0xbd16c32c,0x3f7f9c18,0xbd621469,0x3fff4e6d,0xbe16a905,0x3f7eea9d,0xbdbc3ac3,0x3f7e70b0,0xbde1bc2e,0x3f7de0b1,0xbe039502,
0x3f800000,0x0,0x3f7fe129,0xbcfb49ba,0x3f7f84ab,0xbd7b2b74,0x3f7eea9d,0xbdbc3ac3,0x3ffe1324,0xbe7ab273,0x3f7cfe73,0xbe1c76de,0x3f7baccd,0xbe3b6ecf,0x3f7a1e84,0xbe5a3997,
0x3f800000,0x0,0x3f7fc38f,0xbd2fe007,0x3f7f0e58,0xbdafb680,0x3f7de0b1,0xbe039502,0x3ffc3b28,0xbeaf10a2,0x3f7a1e84,0xbe5a3997,0x3f778bc5,0xbe827dc0,0x3f748422,0xbe97a117,
0x3f800000,0x0,0x3f7f9c18,0xbd621469,0x3f7e70b0,0xbde1bc2e,0x3f7c7eb0,0xbe28defc,0x3ff9c79d,0xbee05c13,0x3f764d97,0xbe8b9507,0x3f721352,0xbea68f12,0x3f6d1c1d,0xbec1071e,
0x3f800000,0x0,0x3f7f6ac7,0xbd8a200a,0x3f7dabcc,0xbe09cf86,0x3f7ac516,0xbe4dee60,0x3ff6ba07,0xbf088e93,0x3f718f57,0xbea986c4,0x3f6b4b0c,0xbec9b953,0x3f63f473,0xbee900b7,
0x3f800000,0x0,0x3f7f2f9d,0xbda3308c,0x3f7cbfc9,0xbe22abb6,0x3f78b47b,0xbe72b651,0x3ff31447,0xbf209ae5,0x3f6be858,0xbec6d529,0x3f633c5a,0xbeebcbbb,0x3f591e6a,0xbf07a136,
0x3f800000,0x0,0x3f7eea9d,0xbdbc3ac3,0x3f7baccd,0xbe3b6ecf,0x3f764d97,0xbe8b9507,0x3feed89e,0xbf38442a,0x3f655e0b,0xbee363fa,0x3f59f26a,0xbf064b82,0x3f4cae79,0xbf19c200,
0x3f800000,0x0,0x3f7e9bc9,0xbdd53db9,0x3f7a7302,0xbe541501,0x3f73913f,0xbe9d9e78,0x3fea09a7,0xbf4f7bca,0x3f5df6be,0xbeff17b2,0x3f4f7a1f,0xbf15f6d9,0x3f3ebc1b,0xbf2ac082,
0x3f800000,0x0,0x3f7e4323,0xbdee3876,0x3f791298,0xbe6c9a7f,0x3f708066,0xbeaf713a,0x3fe4aa59,0xbf663375,0x3f55b993,0xbf0cead0,0x3f43e200,0xbf24d225,0x3f2f61a5,0xbf3a7ca4,
0x3f800000,0x0,0x3f7de0b1,0xbe039502,0x3f778bc5,0xbe827dc0,0x3f6d1c1d,0xbec1071e,0x3fdebe05,0xbf7c5d27,0x3f4cae79,0xbf19c200,0x3f373a23,0xbf32c8c9,0x3f1ebc12,0xbf48d8b3,
0x3f800000,0x0,0x3f7d7474,0xbe1008b7,0x3f75dec6,0xbe8e9a22,0x3f696591,0xbed25a09,0x3fd84853,0xbf88f59b,0x3f42de29,0xbf26050a,0x3f299415,0xbf3fc767,0x3f0cead0,0xbf55b993,
0x3f800000,0x0,0x3f7cfe73,0xbe1c76de,0x3f740bdd,0xbe9aa086,0x3f655e0b,0xbee363fa,0x3fd14d3d,0xbf93682a,0x3f385216,0xbf31a81d,0x3f1b02c6,0xbf4bbbf8,0x3ef41f07,0xbf6106f2,
0x3f800000,0x0,0x3f7c7eb0,0xbe28defc,0x3f721352,0xbea68f12,0x3f6106f2,0xbef41f07,0x3fc9d112,0xbf9d7fd1,0x3f2d1469,0xbf3ca003,0x3f0b9a6b,0xbf5695e5,0x3ecc9b8b,0xbf6aab7b,
0x3f800000,0x0,0x3f7bf531,0xbe354098,0x3f6ff573,0xbeb263ef,0x3f5c61c7,0xbf0242b1,0x3fc1d870,0xbfa73656,0x3f212ff9,0xbf46e22a,0x3ef6e0cb,0xbf604621,0x3ea395c5,0xbf7294f8,
0x3f800000,0x0,0x3f7b61fc,0xbe419b37,0x3f6db293,0xbebe1d4a,0x3f577026,0xbf0a48ad,0x3fb96842,0xbfb085bb,0x3f14b039,0xbf5064af,0x3ed53641,0xbf68bf3c,0x3e72b651,0xbf78b47b,
0x3f800000,0x0,0x3f7ac516,0xbe4dee60,0x3f6b4b0c,0xbec9b953,0x3f5233c6,0xbf121eb0,0x3fb085bb,0xbfb96842,0x3f07a136,0xbf591e6a,0x3eb263ef,0xbf6ff573,0x3e1c76de,0xbf7cfe73,
0x3f800000,0x0,0x3f7a1e84,0xbe5a3997,0x3f68bf3c,0xbed53641,0x3f4cae79,0xbf19c200,0x3fa73656,0xbfc1d870,0x3ef41f07,0xbf6106f2,0x3e8e9a22,0xbf75dec6,0x3d8a200a,0xbf7f6ac7,
0x3f800000,0x0,0x3f796e4e,0xbe667c66,0x3f660f88,0xbee0924f,0x3f46e22a,0xbf212ff9,0x3f9d7fd1,0xbfc9d112,0x3ed8106b,0xbf6816a8,0x3e541501,0xbf7a7302,0xbc96c9b6,0xbf7ff4e6,
0x3f800000,0x0,0x3f78b47b,0xbe72b651,0x3f633c5a,0xbeebcbbb,0x3f40d0da,0xbf286605,0x3f93682a,0xbfd14d3d,0x3ebb31a0,0xbf6e46be,0x3e09cf86,0xbf7dabcc,0xbdd53db9,0xbf7e9bc9,
0x3f800000,0x0,0x3f77f110,0xbe7ee6e1,0x3f604621,0xbef6e0cb,0x3f3a7ca4,0xbf2f61a5,0x3f88f59b,0xbfd84853,0x3e9d9e78,0xbf73913f,0x3d7b2b74,0xbf7f84ab,0xbe419b37,0xbf7b61fc,
0x3f800000,0x0,0x3f772417,0xbe8586ce,0x3f5d2d53,0xbf00e7e4,0x3f33e7bc,0xbf36206c,0x3f7c5d27,0xbfdebe05,0x3e7ee6e1,0xbf77f110,0xbc490e90,0xbf7ffb11,0xbe8b9507,0xbf764d97,
0x3f800000,0x0,0x3f764d97,0xbe8b9507,0x3f59f26a,0xbf064b82,0x3f2d1469,0xbf3ca003,0x3f663375,0xbfe4aa59,0x3e419b37,0xbf7b61fc,0xbdafb680,0xbf7f0e58,0xbeb554ec,0xbf6f6830,
0x3f800000,0x0,0x3f756d97,0xbe919ddd,0x3f5695e5,0xbf0b9a6b,0x3f26050a,0xbf42de29,0x3f4f7bca,0xbfea09a7,0x3e039502,0xbf7de0b1,0xbe22abb6,0xbf7cbfc9,0xbeddbe79,0xbf66becc,
0x3f800000,0x0,0x3f748422,0xbe97a117,0x3f531849,0xbf10d3cd,0x3f1ebc12,0xbf48d8b3,0x3f38442a,0xbfeed89e,0x3d8a200a,0xbf7f6ac7,0xbe6c9a7f,0xbf791298,0xbf0242b1,0xbf5c61c7,
0x3f800000,0x0,0x3f73913f,0xbe9d9e78,0x3f4f7a1f,0xbf15f6d9,0x3f173c07,0xbf4e8d90,0x3f209ae5,0xbff31447,0x3bc90f88,0xbf7ffec4,0xbe9aa086,0xbf740bdd,0xbf14b039,0xbf5064af,
0x3f800000,0x0,0x3f7294f8,0xbea395c5,0x3f4bbbf8,0xbf1b02c6,0x3f0f8784,0xbf53fac3,0x3f088e93,0xbff6ba07,0xbd621469,0xbf7f9c18,0xbebe1d4a,0xbf6db293,0xbf26050a,0xbf42de29,
0x3f800000,0x0,0x3f718f57,0xbea986c4,0x3f47de65,0xbf1ff6cb,0x3f07a136,0xbf591e6a,0x3ee05c13,0xbff9c79d,0xbdee3876,0xbf7e4323,0xbee0924f,0xbf660f88,0xbf36206c,0xbf33e7bc,
0x3f800000,0x0,0x3f708066,0xbeaf713a,0x3f43e200,0xbf24d225,0x3eff17b2,0xbf5df6be,0x3eaf10a2,0xbffc3b28,0xbe354098,0xbf7bf531,0xbf00e7e4,0xbf5d2d53,0xbf44e3f5,0xbf239da9,
0x3f800000,0x0,0x3f6f6830,0xbeb554ec,0x3f3fc767,0xbf299415,0x3eee9479,0xbf628210,0x3e7ab273,0xbffe1324,0xbe72b651,0xbf78b47b,0xbf10d3cd,0xbf531849,0xbf5233c6,0xbf121eb0,
0x3f800000,0x0,0x3f6e46be,0xbebb31a0,0x3f3b8f3b,0xbf2e3bde,0x3eddbe79,0xbf66becc,0x3e16a905,0xbfff4e6d,0xbe97a117,0xbf748422,0xbf1ff6cb,0xbf47de65,0xbf5df6be,0xbeff17b2,
0x3f800000,0x0,0x3f6d1c1d,0xbec1071e,0x3f373a23,0xbf32c8c9,0x3ecc9b8b,0xbf6aab7b,0x3d490ab0,0xbfffec43,0xbeb554ec,0xbf6f6830,0xbf2e3bde,0xbf3b8f3b,0xbf6816a8,0xbed8106b,
0x3f800000,0x0,0x3f7ffd39,0xbc16cb58,0x3f7ff4e6,0xbc96c9b6,0x3f7fe705,0xbce22a7a,0x3fffd397,0xbd96c32c,0x3f7fba9e,0xbd3c6dd5,0x3f7f9c18,0xbd621469,0x3f7f7808,0xbd83db0a,
0x3f800000,0x0,0x3f7ff0e3,0xbcafea69,0x3f7fc38f,0xbd2fe007,0x3f7f7808,0xbd83db0a,0x3fff0e58,0xbe2fb680,0x3f7e868b,0xbddb7d37,0x3f7de0b1,0xbe039502,0x3f7d1cdd,0xbe195be0,
0x3f800000,0x0,0x3f7fdaaf,0xbd0a342f,0x3f7f6ac7,0xbd8a200a,0x3f7eb069,0xbdcefdb7,0x3ffdabcc,0xbe89cf86,0x3f7c5d3a,0xbe2bf804,0x3f7ac516,0xbe4dee60,0x3f78e3d6,0xbe6fa8b2,
0x3f800000,0x0,0x3f7fba9e,0xbd3c6dd5,0x3f7eea9d,0xbdbc3ac3,0x3f7d906e,0xbe0cec4a,0x3ffbaccd,0xbebb6ecf,0x3f7940c0,0xbe698bba,0x3f764d97,0xbe8b9507,0x3f72d4eb,0xbea21887,
0x3f800000,0x0,0x3f7f90b1,0xbd6ea038,0x3f7e4323,0xbdee3876,0x3f7c187a,0xbe3228d4,0x3ff91298,0xbeec9a7f,0x3f75341d,0xbe931f35,0x3f708066,0xbeaf713a,0x3f6afb8c,0xbecb2aae,
0x3f800000,0x0,0x3f7f5ce9,0xbd9064b4,0x3f7d7474,0xbe1008b7,0x3f7a4910,0xbe57278f,0x3ff5dec6,0xbf0e9a22,0x3f703b37,0xbeb0eacb,0x3f696591,0xbed25a09,0x3f61668a,0xbef2bd43,
0x3f800000,0x0,0x3f7f1f49,0xbda973ba,0x3f7c7eb0,0xbe28defc,0x3f7822d1,0xbe7bdba4,0x3ff21352,0xbf268f12,0x3f6a5ad9,0xbece0bea,0x3f6106f2,0xbef41f07,0x3f5627fe,0xbf0c42c9,
0x3f800000,0x0,0x3f7ed7d4,0xbdc27c39,0x3f7b61fc,0xbe419b37,0x3f75a67b,0xbe901c2c,0x3fedb293,0xbf3e1d4a,0x3f6398ac,0xbeea6681,0x3f577026,0xbf0a48ad,0x3f495521,0xbf1e1e22,
0x3f800000,0x0,0x3f7e868b,0xbddb7d37,0x3f7a1e84,0xbe5a3997,0x3f72d4eb,0xbea21887,0x3fe8bf3c,0xbf553641,0x3f5bfb34,0xbf02ef9f,0x3f4cae79,0xbf19c200,0x3f3b0629,0xbf2ecef7,
0x3f800000,0x0,0x3f7e2b72,0xbdf475c0,0x3f78b47b,0xbe72b651,0x3f6faf1b,0xbeb3dca5,0x3fe33c5a,0xbf6bcbbb,0x3f5389c7,0xbf102dd5,0x3f40d0da,0xbf286605,0x3f2b561b,0xbf3e35c5,
0x3f800000,0x0,0x3f7dc68c,0xbe06b26e,0x3f772417,0xbe8586ce,0x3f6c3624,0xbec5625c,0x3fdd2d53,0xbf80e7e4,0x3f4a4c87,0xbf1ce11f,0x3f33e7bc,0xbf36206c,0x3f1a6293,0xbf4c3578,
0x3f800000,0x0,0x3f7d57de,0xbe1324ca,0x3f756d97,0xbe919ddd,0x3f686b39,0xbed6a399,0x3fd695e5,0xbf8b9a6b,0x3f404c5c,0xbf28fd41,0x3f26050a,0xbf42de29,0x3f084b92,0xbf58b3a1,
0x3f800000,0x0,0x3f7cdf6c,0xbe1f917b,0x3f73913f,0xbe9d9e78,0x3f644fac,0xbee79a5d,0x3fcf7a1f,0xbf95f6d9,0x3f3592e7,0xbf34768f,0x3f173c07,0xbf4e8d90,0x3eea6681,0xbf6398ac,
0x3f800000,0x0,0x3f7c5d3a,0xbe2bf804,0x3f718f57,0xbea986c4,0x3f5fe4e9,0xbef840c8,0x3fc7de65,0xbf9ff6cb,0x3f2a2a80,0xbf3f41fc,0x3f07a136,0xbf591e6a,0x3ec27b55,0xbf6cd007,
0x3f800000,0x0,0x3f7bd14d,0xbe3857ec,0x3f6f6830,0xbeb554ec,0x3f5b2c79,0xbf044889,0x3fbfc767,0xbfa99415,0x3f1e1e22,0xbf495521,0x3eee9479,0xbf628210,0x3e9920fe,0xbf74484b,
0x3f800000,0x0,0x3f7b3bab,0xbe44b0b9,0x3f6d1c1d,0xbec1071e,0x3f5627fe,0xbf0c42c9,0x3fb73a23,0xbfb2c8c9,0x3f11796b,0xbf52a649,0x3ecc9b8b,0xbf6aab7b,0x3e5d4b1a,0xbf79f35e,
0x3f800000,0x0,0x3f7a9c59,0xbe5101f1,0x3f6aab7b,0xbecc9b8b,0x3f50d937,0xbf140c5f,0x3fae3bde,0xbfbb8f3b,0x3f044889,0xbf5b2c79,0x3ea986c4,0xbf718f57,0x3e06b26e,0xbf7dc68c,
0x3f800000,0x0,0x3f79f35e,0xbe5d4b1a,0x3f6816a8,0xbed8106b,0x3f4b41fa,0xbf1ba299,0x3fa4d225,0xbfc3e200,0x3eed3063,0xbf62df7b,0x3e8586ce,0xbf772417,0x3d3c6dd5,0xbf7fba9e,
0x3f800000,0x0,0x3f7940c0,0xbe698bba,0x3f655e0b,0xbee363fa,0x3f456439,0xbf2302d3,0x3f9b02c6,0xbfcbbbf8,0x3ed0eb2a,0xbf69b7e4,0x3e419b37,0xbf7b61fc,0xbd2351cb,0xbf7fcbe2,
0x3f800000,0x0,0x3f788486,0xbe75c35a,0x3f628210,0xbeee9479,0x3f3f41fc,0xbf2a2a80,0x3f90d3cd,0xbfd31849,0x3eb3dca5,0xbf6faf1b,0x3dee3876,0xbf7e4323,0xbe007745,0xbf7dfa38,
0x3f800000,0x0,0x3f77beb7,0xbe80f8c0,0x3f5f8327,0xbef9a02d,0x3f38dd65,0xbf311722,0x3f864b82,0xbfd9f26a,0x3e9620d2,0xbf74bf62,0x3d2fe007,0xbf7fc38f,0xbe57278f,0xbf7a4910,
0x3f800000,0x0,0x3f76ef5b,0xbe870ada,0x3f5c61c7,0xbf0242b1,0x3f3238aa,0xbf37c655,0x3f76e0cb,0xbfe04621,0x3e6fa8b2,0xbf78e3d6,0xbcfb49ba,0xbf7fe129,0xbe9620d2,0xbf74bf62,
0x3f800000,0x0,0x3f76167a,0xbe8d17c0,0x3f591e6a,0xbf07a136,0x3f2b561b,0xbf3e35c5,0x3f60924f,0xbfe60f88,0x3e3228d4,0xbf7c187a,0xbdd53db9,0xbf7e9bc9,0xbebf926f,0xbf6d67a1,
0x3f800000,0x0,0x3f75341d,0xbe931f35,0x3f55b993,0xbf0cead0,0x3f24381a,0xbf446337,0x3f49b953,0xbfeb4b0c,0x3de7fa9a,0xbf7e5a38,0xbe354098,0xbf7bf531,0xbee79a5d,0xbf644fac,
0x3f800000,0x0,0x3f74484b,0xbe9920fe,0x3f5233c6,0xbf121eb0,0x3f1ce11f,0xbf4a4c87,0x3f3263ef,0xbfeff573,0x3d55880e,0xbf7fa6e3,0xbe7ee6e1,0xbf77f110,0xbf06f686,0xbf5988ad,
0x3f800000,0x0,0x3f73530e,0xbe9f1cdf,0x3f4e8d90,0xbf173c07,0x3f1553b7,0xbf4fefa8,0x3f1aa086,0xbff40bdd,0xbc16cb58,0xbf7ffd39,0xbea395c5,0xbf7294f8,0xbf19210f,0xbf4d26fd,
0x3f800000,0x0,0x3f725470,0xbea5129f,0x3f4ac77f,0xbf1c420c,0x3f0d9281,0xbf554aa4,0x3f027dc0,0xbff78bc5,0xbd9064b4,0xbf7f5ce9,0xbec6d529,0xbf6be858,0xbf2a2a80,0xbf3f41fc,
0x3f800000,0x0,0x3f714c7a,0xbeab0201,0x3f46e22a,0xbf212ff9,0x3f05a02c,0xbf5a5ba0,0x3ed41501,0xbffa7302,0xbe06b26e,0xbf7dc68c,0xbee900b7,0xbf63f473,0xbf39f2ac,0xbf2ff3e6,
0x3f800000,0x0,0x3f703b37,0xbeb0eacb,0x3f42de29,0xbf26050a,0x3efafef7,0xbf5f20db,0x3ea2abb6,0xbffcbfc9,0xbe44b0b9,0xbf7b3bab,0xbf04f484,0xbf5ac450,0xbf485bca,0xbf1f599f,
0x3f800000,0x0,0x3f6f20b0,0xbeb6ccc3,0x3f3ebc1b,0xbf2ac082,0x3eea6681,0xbf6398ac,0x3e61bc2e,0xbffe70b0,0xbe80f8c0,0xbf77beb7,0xbf14b039,0xbf5064af,0xbf554aa4,0xbf0d9281,
0x3f800000,0x0,0x3f6dfcf2,0xbebca7af,0x3f3a7ca4,0xbf2f61a5,0x3ed97cb9,0xbf67c187,0x3dfb2b74,0xbfff84ab,0xbe9f1cdf,0xbf73530e,0xbf239da9,0xbf44e3f5,0xbf60a6cf,0xbef58035,
0x3f800000,0x0,0x3f6cd007,0xbec27b55,0x3f36206c,0xbf33e7bc,0x3ec8477c,0xbf6b99fb,0x3cc90e90,0xbffffb11,0xbebca7af,0xbf6dfcf2,0xbf31a81d,0xbf385216,0xbf6a5ad9,0xbece0bea,
0x3f800000,0x0,0x0,0x0,0x0,0x0,0x0,0x0,0x0,0x0,0x0,0x0,0x0,0x0,0x0,0x0,
0x0,0x0,0x0,0x0,0x0,0x0,0x0,0x0,0x0,0x0,0x0,0x0,0x0,0x0,0x0,0x0,
0x0,0x0,0x3e000000,0xbf20dff7,0x3ed0c429,0x0,0x3e000000,0x3e61f78b,0x3e0a8bd4,0x0,0x3e000000,0x3d5413cd,0x3d5df9ad,0x0,0x3e000000,0x3cf043ab,
0x0,0x0,0x3e000000,0x3ccbafaf,0xbd5df9ad,0x0,0x3e000000,0x3cf043ab,0xbe0a8bd4,0x0,0x3e000000,0x3d5413cd,0xbed0c429,0x0,0x3e000000,0x3e61f78b,
0x0,0x0,0x0,0x0,0x3f000000,0x0,0x0,0x3f000000,0x0,0x0,0x0,0x0,0x0,0x0,0x0,0x0,
0x0,0x0,0x0,0x0,0x0,0x0,0x0,0x0,0x0,0x0,0x0,0x0,0x3f000000,0x0,0x0,0xbf000000,
0x0,0x0,0x3e000000,0xbe3f90c7,0xbe8b7e3f,0x0,0x3e000000,0xbeb641af,0x3ea73d75,0x0,0x3e000000,0x3e9a827a,0x3da61ad1,0x0,0x3e000000,0x3dd906bd,
0x0,0x0,0x3e000000,0x3dab0dc1,0xbda61ad1,0x0,0x3e000000,0x3dd906bd,0xbea73d75,0x0,0x3e000000,0x3e9a827a,0x3e8b7e3f,0x0,0x3e000000,0xbeb641af,
0x0,0x0,0x0,0x0,0x0,0x0,0x0,0x0,0x3f000000,0x0,0x0,0x3f000000,0x0,0x0,0x0,0x0,
0x0,0x0,0x0,0x0,0x0,0x0,0x0,0x0,0x3f000000,0x0,0x0,0xbf000000,0x0,0x0,0x0,0x0,
0x0,0x0,0x3e000000,0xbdab0dc1,0xbda61ad1,0x0,0x3e000000,0xbdd906bd,0xbea73d75,0x0,0x3e000000,0xbe9a827a,0x3e8b7e3f,0x0,0x3e000000,0x3eb641af,
0x0,0x0,0x3e000000,0x3e3f90c7,0xbe8b7e3f,0x0,0x3e000000,0x3eb641af,0x3ea73d75,0x0,0x3e000000,0xbe9a827a,0x3da61ad1,0x0,0x3e000000,0xbdd906bd,
0x0,0x0,0x0,0x0,0x0,0x0,0x0,0x0,0x0,0x0,0x0,0x0,0x3f000000,0x0,0x0,0x3f000000,
0x0,0x0,0x0,0x0,0x3f000000,0x0,0x0,0xbf000000,0x0,0x0,0x0,0x0,0x0,0x0,0x0,0x0,
0x0,0x0,0x3e000000,0xbccbafaf,0xbd5df9ad,0x0,0x3e000000,0xbcf043ab,0xbe0a8bd4,0x0,0x3e000000,0xbd5413cd,0xbed0c429,0x0,0x3e000000,0xbe61f78b,
0x0,0x0,0x3e000000,0x3f20dff7,0x3ed0c429,0x0,0x3e000000,0xbe61f78b,0x3e0a8bd4,0x0,0x3e000000,0xbd5413cd,0x3d5df9ad,0x0,0x3e000000,0xbcf043ab,
};

struct Params {
    const __nv_bfloat16 *wr, *wi, *lre, *lim, *ldt, *dsk;
    float* out;
};

struct cf { float x, y; };
#define YIELD() asm volatile("pmevent 1;")
#define YS 15
#define YIELD_S1() do { if (YS & 1) YIELD(); } while (0)
#define YIELD_S2() do { if (YS & 2) YIELD(); } while (0)
#define YIELD_S3() do { if (YS & 4) YIELD(); } while (0)
__device__ __forceinline__ uint32_t smem_u32(const void* p) { return (uint32_t)__cvta_generic_to_shared(p); }
__device__ __forceinline__ void mbar_init(uint32_t a, uint32_t c) { asm volatile("mbarrier.init.shared::cta.b64 [%0], %1;" ::"r"(a), "r"(c) : "memory"); }
__device__ __forceinline__ void mbar_expect_tx(uint32_t a, uint32_t b) { asm volatile("mbarrier.arrive.expect_tx.shared::cta.b64 _, [%0], %1;" ::"r"(a), "r"(b) : "memory"); }
__device__ __forceinline__ void mbar_arrive(uint32_t a) { asm volatile("mbarrier.arrive.shared::cta.b64 _, [%0];" ::"r"(a) : "memory"); }
__device__ __forceinline__ void warp_arrive(uint32_t a) {
    __syncwarp();
    asm volatile("{.reg .pred p; elect.sync _|p, 0xffffffff; @p mbarrier.arrive.shared::cta.b64 _, [%0];}" ::"r"(a) : "memory");
}
__device__ __forceinline__ void mbar_wait(uint32_t a, uint32_t ph) {
    asm volatile("{.reg .pred p, c; .reg .b32 n; mov.b32 n, 0;\n"
                 "W: mbarrier.try_wait.parity.shared::cta.b64 p, [%0], %1; add.u32 n, n, 1; setp.lt.u32 c, n, %2; not.pred p, p; and.pred p, p, c; @p bra W;}" ::"r"(a), "r"(ph), "n"(SPIN_LIMIT) : "memory");
}
__device__ __forceinline__ unsigned ld_rlx(const unsigned* p) { unsigned v; asm volatile("ld.relaxed.gpu.global.u32 %0, [%1];" : "=r"(v) : "l"(p) : "memory"); return v; }
__device__ __forceinline__ void wait_cnt(const unsigned* p, unsigned target) {
    unsigned n = 0;
    while ((int)(ld_rlx(p) - target) < 0 && ++n < SPIN_LIMIT) __nanosleep(20);
}
__device__ __forceinline__ void red_hint(unsigned* p) { asm volatile("red.relaxed.gpu.global.add.u32 [%0], 1;" ::"l"(p) : "memory"); }
__device__ __forceinline__ void fence_async_sm() { asm volatile("fence.proxy.async.shared::cta;" ::: "memory"); }
#define bar_sync(id, n) asm volatile("bar.sync %0, %1;" ::"n"(id), "n"(n) : "memory")
#define bar_arrive(id, n) asm volatile("bar.arrive %0, %1;" ::"n"(id), "n"(n) : "memory")
__device__ __forceinline__ bool elect_one() {
    uint32_t r;
    asm volatile("{.reg .pred p; elect.sync _|p, 0xffffffff; selp.u32 %0, 1, 0, p;}" : "=r"(r));
    return r != 0;
}

__device__ __forceinline__ void tma2d(uint32_t dst, const CUtensorMap* m, int c0, int c1, uint32_t bar) {
    asm volatile("cp.async.bulk.tensor.2d.shared::cluster.global.mbarrier::complete_tx::bytes [%0], [%1, {%3,%4}], [%2];" ::"r"(dst), "l"(m), "r"(bar), "r"(c0), "r"(c1) : "memory");
}
__device__ __forceinline__ void tma3d(uint32_t dst, const CUtensorMap* m, int c0, int c1, int c2, uint32_t bar) {
    asm volatile("cp.async.bulk.tensor.3d.shared::cluster.global.mbarrier::complete_tx::bytes [%0], [%1, {%3,%4,%5}], [%2];" ::"r"(dst), "l"(m), "r"(bar), "r"(c0), "r"(c1), "r"(c2) : "memory");
}
__device__ __forceinline__ void tma4d_mc(uint32_t dst, const CUtensorMap* m, int c0, int c1, int c2, int c3, uint32_t bar) {
    asm volatile("cp.async.bulk.tensor.4d.shared::cluster.global.mbarrier::complete_tx::bytes.multicast::cluster [%0], [%1, {%3,%4,%5,%6}], [%2], %7;" ::"r"(dst), "l"(m), "r"(bar), "r"(c0), "r"(c1), "r"(c2), "r"(c3), "h"((uint16_t)3) : "memory");
}
__device__ __forceinline__ void tma4d(uint32_t dst, const CUtensorMap* m, int c0, int c1, int c2, int c3, uint32_t bar) {
    asm volatile("cp.async.bulk.tensor.4d.shared::cluster.global.mbarrier::complete_tx::bytes [%0], [%1, {%3,%4,%5,%6}], [%2];" ::"r"(dst), "l"(m), "r"(bar), "r"(c0), "r"(c1), "r"(c2), "r"(c3) : "memory");
}
__device__ __forceinline__ void tma2d_st(const CUtensorMap* m, int c0, int c1, uint32_t src) {
    asm volatile("cp.async.bulk.tensor.2d.global.shared::cta.bulk_group [%0, {%2,%3}], [%1];" ::"l"(m), "r"(src), "r"(c0), "r"(c1) : "memory");
}
__device__ __forceinline__ void tma5d(uint32_t dst, const CUtensorMap* m, int c0, int c1, int c2, int c3, int c4, uint32_t bar) {
    asm volatile("cp.async.bulk.tensor.5d.shared::cluster.global.mbarrier::complete_tx::bytes [%0], [%1, {%3,%4,%5,%6,%7}], [%2];" ::"r"(dst), "l"(m), "r"(bar), "r"(c0), "r"(c1), "r"(c2), "r"(c3), "r"(c4) : "memory");
}
__device__ __forceinline__ void bulk_ld(uint32_t dst, const void* src, uint32_t n, uint32_t bar) {
    asm volatile("cp.async.bulk.shared::cluster.global.mbarrier::complete_tx::bytes [%0], [%1], %2, [%3];" ::"r"(dst), "l"(src), "r"(n), "r"(bar) : "memory");
}
__device__ __forceinline__ void bulk_st(void* dst, uint32_t src, uint32_t n) {
    asm volatile("cp.async.bulk.global.shared::cta.bulk_group [%0], [%1], %2;" ::"l"(dst), "r"(src), "r"(n) : "memory");
}
__device__ __forceinline__ void bulk_commit() { asm volatile("cp.async.bulk.commit_group;" ::: "memory"); }
__device__ __forceinline__ void bulk_wait_read() { asm volatile("cp.async.bulk.wait_group.read 0;" ::: "memory"); }
__device__ __forceinline__ void bulk_wait_all() { asm volatile("cp.async.bulk.wait_group 0;" ::: "memory"); }
__device__ __forceinline__ void stsm4(uint32_t a, uint32_t r0, uint32_t r1, uint32_t r2, uint32_t r3) {
    asm volatile("stmatrix.sync.aligned.m8n8.x4.shared.b16 [%0], {%1,%2,%3,%4};" ::"r"(a), "r"(r0), "r"(r1), "r"(r2), "r"(r3) : "memory");
}
__device__ __forceinline__ void sts128(uint32_t a, uint32_t r0, uint32_t r1, uint32_t r2, uint32_t r3) {
    asm volatile("st.shared.v4.b32 [%0], {%1,%2,%3,%4};" ::"r"(a), "r"(r0), "r"(r1), "r"(r2), "r"(r3) : "memory");
}
__device__ __forceinline__ void lds128f(uint32_t a, float& x, float& y, float& z, float& u) { asm volatile("ld.shared.v4.f32 {%0,%1,%2,%3}, [%4];" : "=f"(x), "=f"(y), "=f"(z), "=f"(u) : "r"(a) : "memory"); }
__device__ __forceinline__ cf lds_cf(uint32_t a) { cf v; asm volatile("ld.shared.v2.f32 {%0,%1}, [%2];" : "=f"(v.x), "=f"(v.y) : "r"(a) : "memory"); return v; }
__device__ __forceinline__ void stg128(const void* a, uint32_t r0, uint32_t r1, uint32_t r2, uint32_t r3) {
    asm volatile("st.global.v4.b32 [%0], {%1,%2,%3,%4};" ::"l"(a), "r"(r0), "r"(r1), "r"(r2), "r"(r3) : "memory");
}
__device__ __forceinline__ int fresh_lane() { int v; asm volatile("mov.u32 %0, %%laneid;" : "=r"(v)); return v; }
__device__ __forceinline__ uint32_t opaque32(uint32_t v) { asm volatile("" : "+r"(v)); return v; }
__device__ __forceinline__ const uint8_t* padd(const void* base, uint32_t off) {
    uint64_t r;
    asm("{.reg .u32 l, h; mov.b64 {l, h}, %1; add.cc.u32 l, l, %2; addc.u32 h, h, 0; mov.b64 %0, {l, h};}" : "=l"(r) : "l"(base), "r"(off));
    return (const uint8_t*)r;
}
template <int N, int STRIDE> __device__ __forceinline__ void ldtab(uint32_t (&v)[4 * N], uint32_t off) {
    const uint8_t* a = padd(g_tab, off);
#pragma unroll
    for (int i = 0; i < N; i++)
        asm volatile("ld.global.nc.v4.b32 {%0,%1,%2,%3}, [%4];" : "=r"(v[4 * i]), "=r"(v[4 * i + 1]), "=r"(v[4 * i + 2]), "=r"(v[4 * i + 3]) : "l"(a + i * STRIDE));
}
template <int STRIDE> __device__ __forceinline__ void ldtab_cf(cf (&t)[8], uint32_t off) {
    uint32_t v[16];
    ldtab<4, STRIDE>(v, off);
#pragma unroll
    for (int i = 0; i < 8; i++) t[i] = {__uint_as_float(v[2 * i]), __uint_as_float(v[2 * i + 1])};
}
__device__ __forceinline__ uint32_t lds16(uint32_t a) { uint32_t v; asm volatile("ld.shared.u16 %0, [%1];" : "=r"(v) : "r"(a)); return v; }
__device__ __forceinline__ unsigned get_epoch(uint32_t bars) {
    mbar_wait(bars + B_EP, 0);
    unsigned e;
    asm volatile("ld.shared.u32 %0, [%1];" : "=r"(e) : "r"(bars + B_EPOCH) : "memory");
    return e;
}
__device__ __forceinline__ void sts64(uint32_t a, uint32_t x, uint32_t y) { asm volatile("st.shared.v2.b32 [%0], {%1,%2};" ::"r"(a), "r"(x), "r"(y) : "memory"); }
__device__ __forceinline__ uint32_t pk(float lo, float hi) { uint32_t r; asm("cvt.rn.bf16x2.f32 %0, %1, %2;" : "=r"(r) : "f"(hi), "f"(lo)); return r; }
__device__ __forceinline__ float bf2f(unsigned short v) { return __uint_as_float((uint32_t)v << 16); }

__device__ __forceinline__ uint64_t mkdesc(uint32_t addr, uint32_t lbo, uint32_t sbo, uint32_t swz) {
    return (uint64_t)((addr & 0x3FFFF) >> 4) | ((uint64_t)(lbo >> 4) << 16) | ((uint64_t)(sbo >> 4) << 32) | ((uint64_t)swz << 62);
}
__device__ __forceinline__ uint64_t opaque(uint64_t v) { asm volatile("" : "+l"(v)); return v; }
__device__ __forceinline__ void wg_fence() { asm volatile("wgmma.fence.sync.aligned;" ::: "memory"); }
__device__ __forceinline__ void wg_commit() { asm volatile("wgmma.commit_group.sync.aligned;" ::: "memory"); }
template <int N> __device__ __forceinline__ void wg_wait() { asm volatile("wgmma.wait_group.sync.aligned %0;" ::"n"(N) : "memory"); }
template <int N> __device__ __forceinline__ void pin(float (&d)[N]) {
#pragma unroll
    for (int i = 0; i < N; i++) asm volatile("" : "+f"(d[i])::"memory");
}
template <int N> __device__ __forceinline__ void pinu(uint32_t (&d)[N]) {
#pragma unroll
    for (int i = 0; i < N; i++) asm volatile("" : "+r"(d[i])::"memory");
}

#define R8(d, o) "+f"(d[o]), "+f"(d[o + 1]), "+f"(d[o + 2]), "+f"(d[o + 3]), "+f"(d[o + 4]), "+f"(d[o + 5]), "+f"(d[o + 6]), "+f"(d[o + 7])
#define L8 "%0,%1,%2,%3,%4,%5,%6,%7"
#define L32 L8 ",%8,%9,%10,%11,%12,%13,%14,%15,%16,%17,%18,%19,%20,%21,%22,%23,%24,%25,%26,%27,%28,%29,%30,%31"
#define L56 L32 ",%32,%33,%34,%35,%36,%37,%38,%39,%40,%41,%42,%43,%44,%45,%46,%47,%48,%49,%50,%51,%52,%53,%54,%55"
#define L64 L56 ",%56,%57,%58,%59,%60,%61,%62,%63"

template <int O, int TA, int TB, int N> __device__ __forceinline__ void mma128_ss(float (&d)[N], uint64_t da, uint64_t db, int sc) {
    asm volatile("{.reg .pred p; setp.ne.b32 p, %66, 0;\n"
                 "wgmma.mma_async.sync.aligned.m64n128k16.f32.bf16.bf16 {" L64 "}, %64, %65, p, 1, 1, %67, %68;}"
                 : R8(d, O), R8(d, O + 8), R8(d, O + 16), R8(d, O + 24), R8(d, O + 32), R8(d, O + 40), R8(d, O + 48), R8(d, O + 56)
                 : "l"(da), "l"(db), "r"(sc), "n"(TA), "n"(TB));
}
template <int O, int TB> __device__ __forceinline__ void mma128_rs(float (&d)[128], uint32_t a0, uint32_t a1, uint32_t a2, uint32_t a3, uint64_t db, int sc) {
    asm volatile("{.reg .pred p; setp.ne.b32 p, %69, 0;\n"
                 "wgmma.mma_async.sync.aligned.m64n128k16.f32.bf16.bf16 {" L64 "}, {%64,%65,%66,%67}, %68, p, 1, 1, %70;}"
                 : R8(d, O), R8(d, O + 8), R8(d, O + 16), R8(d, O + 24), R8(d, O + 32), R8(d, O + 40), R8(d, O + 48), R8(d, O + 56)
                 : "r"(a0), "r"(a1), "r"(a2), "r"(a3), "l"(db), "r"(sc), "n"(TB));
}
template <int TB> __device__ __forceinline__ void mma64_rs(float (&d)[32], uint32_t a0, uint32_t a1, uint32_t a2, uint32_t a3, uint64_t db, int sc) {
    asm volatile("{.reg .pred p; setp.ne.b32 p, %37, 0;\n"
                 "wgmma.mma_async.sync.aligned.m64n64k16.f32.bf16.bf16 {" L32 "}, {%32,%33,%34,%35}, %36, p, 1, 1, %38;}"
                 : R8(d, 0), R8(d, 8), R8(d, 16), R8(d, 24)
                 : "r"(a0), "r"(a1), "r"(a2), "r"(a3), "l"(db), "r"(sc), "n"(TB));
}
__device__ __forceinline__ void mma112_ss(float (&d)[64], uint64_t da, uint64_t db, int sc) {
    asm volatile("{.reg .pred p; setp.ne.b32 p, %58, 0;\n"
                 "wgmma.mma_async.sync.aligned.m64n112k16.f32.bf16.bf16 {" L56 "}, %56, %57, p, 1, 1, 0, 1;}"
                 : R8(d, 8), R8(d, 16), R8(d, 24), R8(d, 32), R8(d, 40), R8(d, 48), R8(d, 56)
                 : "l"(da), "l"(db), "r"(sc));
}
__device__ __forceinline__ void mma16_rs(float (&d)[64], uint32_t a0, uint32_t a1, uint32_t a2, uint32_t a3, uint64_t db, int sc) {
    asm volatile("{.reg .pred p; setp.ne.b32 p, %13, 0;\n"
                 "wgmma.mma_async.sync.aligned.m64n16k16.f32.bf16.bf16 {" L8 "}, {%8,%9,%10,%11}, %12, p, 1, 1, 1;}"
                 : R8(d, 0)
                 : "r"(a0), "r"(a1), "r"(a2), "r"(a3), "l"(db), "r"(sc));
}

__device__ __forceinline__ cf cmul(cf a, cf b) { return {fmaf(a.x, b.x, -a.y * b.y), fmaf(a.x, b.y, a.y * b.x)}; }
__device__ __forceinline__ cf cmulc(cf a, cf b) { return {fmaf(a.x, b.x, a.y * b.y), fmaf(a.y, b.x, -a.x * b.y)}; }
__device__ __forceinline__ cf cfma(cf a, cf b, cf c) { return {fmaf(a.x, b.x, fmaf(-a.y, b.y, c.x)), fmaf(a.x, b.y, fmaf(a.y, b.x, c.y))}; }
__device__ __forceinline__ cf csq(cf a) { return {fmaf(a.x, a.x, -a.y * a.y), (a.x * a.y) * 2.f}; }
__device__ __forceinline__ cf csel(int c, cf a, cf b) {
    cf r;
    asm("{.reg .pred p; setp.ne.s32 p, %2, 0; selp.f32 %0, %3, %5, p; selp.f32 %1, %4, %6, p;}" : "=f"(r.x), "=f"(r.y) : "r"(c), "f"(a.x), "f"(a.y), "f"(b.x), "f"(b.y));
    return r;
}
__device__ __forceinline__ cf cadd(cf a, cf b) { return {a.x + b.x, a.y + b.y}; }
__device__ __forceinline__ cf csub(cf a, cf b) { return {a.x - b.x, a.y - b.y}; }
__device__ __forceinline__ cf twice_minus(cf a, cf s) { return {fmaf(2.f, a.x, -s.x), fmaf(2.f, a.y, -s.y)}; }
__device__ __forceinline__ cf twid(int m, int M) {
    int r = ((m + M / 2) & (M - 1)) - M / 2;
    float s, c;
    __sincosf((float)r * (-6.283185307179586f / (float)M), &s, &c);
    return {c, s};
}
struct c2 { cf a, b; };
#define YP1 2
#define YP3 3
template <int Y> __device__ __forceinline__ void fin(c2& u) { if (Y & 1) asm volatile("pmevent 1;" : "+f"(u.a.x), "+f"(u.a.y), "+f"(u.b.x), "+f"(u.b.y)); }
template <int Y> __device__ __forceinline__ void fin(c2& u, c2& v) {
    if (Y & 2) asm volatile("pmevent 1;" : "+f"(u.a.x), "+f"(u.a.y), "+f"(u.b.x), "+f"(u.b.y), "+f"(v.a.x), "+f"(v.a.y), "+f"(v.b.x), "+f"(v.b.y));
}
__device__ __forceinline__ c2 mul2(c2 u, cf t) { return {cmul(u.a, t), cmul(u.b, t)}; }
__device__ __forceinline__ c2 mul2(c2 u, c2 t) { return {cmul(u.a, t.a), cmul(u.b, t.b)}; }
__device__ __forceinline__ c2 fma2(c2 u, cf t, c2 c) { return {cfma(u.a, t, c.a), cfma(u.b, t, c.b)}; }
__device__ __forceinline__ c2 fma2(c2 u, c2 t, c2 c) { return {cfma(u.a, t.a, c.a), cfma(u.b, t.b, c.b)}; }
__device__ __forceinline__ c2 twm2(c2 u, c2 s) { return {twice_minus(u.a, s.a), twice_minus(u.b, s.b)}; }
template <int Y> __device__ __forceinline__ void bfly(c2& u, c2& v) { const c2 t = u; u = {cadd(t.a, v.a), cadd(t.b, v.b)}; v = {csub(t.a, v.a), csub(t.b, v.b)}; fin<Y>(u, v); }
template <int Y> __device__ __forceinline__ void bfly_mi(c2& u, c2& v) {
    const c2 t = u, z = v;
    u = {{t.a.x + z.a.y, t.a.y - z.a.x}, {t.b.x + z.b.y, t.b.y - z.b.x}};
    v = {{t.a.x - z.a.y, t.a.y + z.a.x}, {t.b.x - z.b.y, t.b.y + z.b.x}};
    fin<Y>(u, v);
}
template <int Y> __device__ __forceinline__ void bfly_s(c2& u, c2& v) {
    const float s = 0.70710678118654752f;
    const c2 t = u, z = v;
    u = {{fmaf(s, z.a.x, t.a.x), fmaf(s, z.a.y, t.a.y)}, {fmaf(s, z.b.x, t.b.x), fmaf(s, z.b.y, t.b.y)}};
    v = {{fmaf(-s, z.a.x, t.a.x), fmaf(-s, z.a.y, t.a.y)}, {fmaf(-s, z.b.x, t.b.x), fmaf(-s, z.b.y, t.b.y)}};
    fin<Y>(u, v);
}
template <int Y, class T> __device__ __forceinline__ void bfly_tw(c2& u0, c2& v0, T t0, c2& u1, c2& v1, T t1) {
    v0 = fma2(v0, t0, u0); fin<Y>(v0);
    v1 = fma2(v1, t1, u1); fin<Y>(v1);
    const c2 a = twm2(u0, v0), b = twm2(u1, v1);
    u0 = v0; u1 = v1; v0 = a; v1 = b;
    fin<Y>(v0, v1);
}
template <bool TW, int Y> __device__ __forceinline__ void dft8(c2 (&v)[8], const cf (&tw)[8]) {
    if (TW) {
#pragma unroll
        for (int n = 1; n < 4; n++) { v[n] = mul2(v[n], tw[n]); fin<Y>(v[n]); }
        bfly_tw<Y>(v[0], v[4], tw[4], v[2], v[6], tw[6]);
        bfly_tw<Y>(v[1], v[5], tw[5], v[3], v[7], tw[7]);
    } else {
#pragma unroll
        for (int n = 0; n < 4; n++) bfly<Y>(v[n], v[n + 4]);
    }
    bfly<Y>(v[0], v[2]); bfly_mi<Y>(v[4], v[6]);
    bfly<Y>(v[1], v[3]); bfly_mi<Y>(v[5], v[7]);
    v[5] = {{v[5].a.x + v[5].a.y, v[5].a.y - v[5].a.x}, {v[5].b.x + v[5].b.y, v[5].b.y - v[5].b.x}};
    v[7] = {{v[7].a.y - v[7].a.x, -v[7].a.x - v[7].a.y}, {v[7].b.y - v[7].b.x, -v[7].b.x - v[7].b.y}};
    fin<Y>(v[5], v[7]);
    bfly<Y>(v[0], v[1]); bfly_s<Y>(v[4], v[5]); bfly_mi<Y>(v[2], v[3]); bfly_s<Y>(v[6], v[7]);
    const c2 t1 = v[1], t3 = v[3];
    v[1] = v[4]; v[4] = t1; v[3] = v[6]; v[6] = t3;
}

__device__ __forceinline__ void gather(uint64_t (&fv)[4], const uint8_t* a, int n) {
    asm volatile("{.reg .pred p0, p1, p2, p3;\n"
                 "setp.ge.s32 p0, %5, 0; setp.ge.s32 p1, %5, 4; setp.ge.s32 p2, %5, 8; setp.ge.s32 p3, %5, 12;\n"
                 "@p0 ld.relaxed.gpu.global.b64 %0, [%4]; @p1 ld.relaxed.gpu.global.b64 %1, [%4+-32768];\n"
                 "@p2 ld.relaxed.gpu.global.b64 %2, [%4+-65536]; @p3 ld.relaxed.gpu.global.b64 %3, [%4+-98304];}"
                 : "+l"(fv[0]), "+l"(fv[1]), "+l"(fv[2]), "+l"(fv[3]) : "l"(a), "r"(n) : "memory");
}
__device__ __forceinline__ cf as_cf(uint64_t v) { cf r; asm("mov.b64 {%0,%1}, %2;" : "=f"(r.x), "=f"(r.y) : "l"(v)); return r; }
template <int H> __device__ __forceinline__ void prescale(float (&u)[64], const float (&d)[128], cf gam) {
#pragma unroll
    for (int i = 0; i < 32; i += 2) {
        const int r = 2 * i + 2 * H;
        c2 v = mul2(c2{{d[r], -d[64 + r]}, {d[r + 1], -d[65 + r]}}, gam);
        if (YS & 2) asm volatile("pmevent 1;" : "+f"(v.a.x), "+f"(v.a.y), "+f"(v.b.x), "+f"(v.b.y));
        u[i] = v.a.x; u[32 + i] = v.a.y; u[i + 1] = v.b.x; u[33 + i] = v.b.y;
    }
}
__device__ __forceinline__ void scan2(const float (&u)[64], cf lam, cf st, const uint8_t* hptr, uint32_t hm, uint32_t hb, uint32_t& keep) {
    uint32_t hp[32];
#pragma unroll
    for (int jj = 0; jj < 4; jj++) {
        cf v[8];
#pragma unroll
        for (int i = 0; i < 8; i++) v[i] = st = cfma(lam, st, {u[8 * jj + i], u[32 + 8 * jj + i]});
        const int o = 8 * jj;
        hp[o] = pk(v[0].x, v[2].x); hp[o + 1] = pk(v[4].x, v[6].x); hp[o + 2] = pk(v[1].x, v[3].x); hp[o + 3] = pk(v[5].x, v[7].x);
        hp[o + 4] = pk(v[0].y, v[2].y); hp[o + 5] = pk(v[4].y, v[6].y); hp[o + 6] = pk(v[1].y, v[3].y); hp[o + 7] = pk(v[5].y, v[7].y);
        hp[o + jj] = (hp[o + jj] & hm) | hb;
        hp[o + 4 + jj] = (hp[o + 4 + jj] & hm) | hb;
        stg128(hptr + (jj >> 1) * 8192 + (jj & 1) * 512, hp[o], hp[o + 1], hp[o + 2], hp[o + 3]);
        stg128(hptr + 16384 + (jj >> 1) * 8192 + (jj & 1) * 512, hp[o + 4], hp[o + 5], hp[o + 6], hp[o + 7]);
        YIELD_S3();
        if (jj > 0) {
#pragma unroll
            for (int i = o - 8; i < o; i += 2) asm volatile("lop3.b32 %0, %0, %1, %2, 0x80;" : "+r"(keep) : "r"(hp[i]), "r"(hp[i + 1]));
        }
    }
}

__device__ __forceinline__ int pos_of(int n) { return (n & 24) + 4 * (n & 1) + ((n >> 1) & 3); }
__device__ __forceinline__ int unit_of(int role, int u, int& slot) {
    const int g = role & 7, w = (role >> 3) & 3, b = role >> 5;
    slot = role >= 128 ? g : (g ? 16 * g + w + 4 * b : 4 * w + b);
    return role >= 128 ? 32 * max(2 * g + u, 1) : (g ? g + 16 * w : ((w & 1) << 4) + ((w & 2) << 2)) + 64 * b + 256 * u;
}
template <int STRIDE> __device__ __forceinline__ bool tags_ok(uint32_t a, uint32_t ep) {
    uint32_t v[4], ok;
#pragma unroll
    for (int i = 0; i < 4; i++) asm volatile("ld.shared.u32 %0, [%1];" : "=r"(v[i]) : "r"(a + i * STRIDE) : "memory");
    asm volatile("{.reg .pred p; .reg .b32 a, b; lop3.b32 a, %1, %2, %5, 0x7e; lop3.b32 b, %3, %4, %5, 0x7e; lop3.b32 a, a, b, 1, 0xa8;\n"
                 "setp.eq.u32 p, a, 0; vote.sync.all.pred p, p, -1; selp.u32 %0, 1, 0, p;}" : "=r"(ok) : "r"(v[0]), "r"(v[1]), "r"(v[2]), "r"(v[3]), "r"(ep));
    return ok;
}
__device__ __forceinline__ void load_w_rows(uint32_t dst, const CUtensorMap* mr, const CUtensorMap* mi, int kap, uint32_t bar) {
#pragma unroll 1
    for (int i = 0; i < 4; i++) {
        __nanosleep(200);
        if (elect_one()) {
            if (!i) mbar_expect_tx(bar, 16 * WPITCH);
            tma2d(dst + i * 4 * WPITCH, (i & 1) ? mi : mr, ((i < 2 ? kap : (512 - kap) & 511) * 1026 >> 4) * 2, 0, bar);
        }
    }
}
template <int K0, int K1> __device__ __forceinline__ void store_v(const uint32_t (&vo)[32], const uint8_t* vp, bool p) {
    if (p) {
#pragma unroll
        for (int k = K0; k < K1; k++)
            asm volatile("st.global.v2.b32 [%0], {%1,%2};" ::"l"(vp + (k >> 2) * (1 << 20) + ((k >> 1) & 1) * 8192 + (k & 1) * (4 * 32768)), "r"(vo[2 * k]), "r"(vo[2 * k + 1]) : "memory");
    }
}
#define SB0 1024
__device__ __forceinline__ uint64_t ring_desc(uint32_t sb, uint32_t off, uint32_t lbo, uint32_t swz) {
    uint64_t d;
    asm volatile("{.reg .b32 z; shr.u32 z, %1, 28; mov.b64 %0, {z, z}; add.u64 %0, %0, %2;}" : "=l"(d) : "r"(sb), "l"(mkdesc(SB0 + off, lbo, 1024, swz)));
    return d;
}
struct Ring {
    uint32_t full, rel;
    uint32_t n;
    bool sig;
};
__device__ __forceinline__ void ring_release(const Ring& r, uint32_t o) {
    if (r.sig) asm volatile("mbarrier.arrive.shared::cluster.b64 _, [%0];" ::"r"(r.rel + o) : "memory");
}
__device__ __forceinline__ void peek(uint32_t a, uint32_t ph) { asm volatile("mbarrier.test_wait.parity.shared::cta.b64 pk, [%0], %1;" ::"r"(a), "r"(ph) : "memory"); }
__device__ __forceinline__ void peek_wait(uint32_t a, uint32_t ph, uint32_t& n) {
    asm volatile("{@pk bra DONE;\n"
                 "LOOP: mbarrier.try_wait.parity.shared::cta.b64 pk, [%1], %2; add.u32 %0, %0, 1; setp.gt.or.u32 pk, %0, %3, pk; @!pk bra LOOP;\n"
                 "DONE: }" : "+r"(n) : "r"(a), "r"(ph), "n"(SPIN_LIMIT) : "memory");
}
#define SL(k) ((k) % NST)
#define PH(k) (((k) / NST) & 1)
#define H64 "%64,%65,%66,%67,%68,%69,%70,%71,%72,%73,%74,%75,%76,%77,%78,%79,%80,%81,%82,%83,%84,%85,%86,%87,%88,%89,%90,%91,%92,%93,%94,%95," \
            "%96,%97,%98,%99,%100,%101,%102,%103,%104,%105,%106,%107,%108,%109,%110,%111,%112,%113,%114,%115,%116,%117,%118,%119,%120,%121,%122,%123,%124,%125,%126,%127"
#define WG_MMA "wgmma.mma_async.sync.aligned.m64n128k16.f32.bf16.bf16 "
#define DESC_B(S, j) "mov.b64 {t, hb}, %130; mov.b64 db, {%137 + 2048 * " #S " + 2 * " #j ", hb};\n"
#define MMA_LO(S, j, p) "add.u64 da, %129, 2048 * " #S " + %136 * " #j ";" DESC_B(S, j) WG_MMA "{" L64 "}, da, db, " #p ", 1, 1, %138, 0;\n"
#define MMA_HI(S, j, p) "add.u64 da, %129, 2048 * " #S " + 512 + %136 * " #j ";\n" WG_MMA "{" H64 "}, da, db, " #p ", 1, 1, %138, 0;\n"
#define STEP(S, P, N, ph, pa, pr, X, Y) \
    "wgmma.fence.sync.aligned;\n" MMA_LO(S, 0, pa) MMA_HI(S, 0, pa) \
    "wgmma.commit_group.sync.aligned; wgmma.wait_group.sync.aligned 1; @" #pr " mbarrier.arrive.shared::cluster.b64 _, [%132 + 8 * " #P "];\n" MMA_LO(S, 1, 1) \
    "mbarrier.test_wait.parity.shared::cta.b64 pk, [%131 + 8 * " #N "], " #ph ";\n" MMA_HI(S, 1, 1) MMA_LO(S, 2, 1) X MMA_HI(S, 2, 1) MMA_LO(S, 3, 1) MMA_HI(S, 3, 1) \
    "wgmma.commit_group.sync.aligned;\n" P4A Y "@pk bra GO" #S ";\n" \
    "WAIT" #S ": mbarrier.try_wait.parity.shared::cta.b64 pk, [%131 + 8 * " #N "], " #ph "; add.u32 %128, %128, 1; setp.gt.or.u32 pk, %128, %139, pk; @!pk bra WAIT" #S ";\n" \
    "GO" #S ":\n" P4B
#define P4A
#define P4B
#define P4I
#define P4O
#define STEP_ARGS(TA) \
    : R8(d, 0), R8(d, 8), R8(d, 16), R8(d, 24), R8(d, 32), R8(d, 40), R8(d, 48), R8(d, 56), \
      R8(d, 64), R8(d, 72), R8(d, 80), R8(d, 88), R8(d, 96), R8(d, 104), R8(d, 112), R8(d, 120), "+r"(r.n) \
    : "l"(ha), "l"(hb), "r"(r.full), "r"(r.rel), "r"((uint32_t)r.sig), "r"(wg), \
      "n"(SB0 / 16 + (TA ? 32 << 16 : 1 << 16)), "n"(TA ? 128 : 2), "n"(SB0 / 16 + 1024 + (1 << 16)), "n"(TA), "n"(SPIN_LIMIT) P4O \
    : "memory"
#define STEP_REGS "{.reg .b32 k, t, ph, hb; .reg .b64 da, db; .reg .pred ps, pl, pa, pr;\n" P4I "setp.ne.u32 ps, %133, 0;\n"
#define FIRST_WAIT "FIRST: mbarrier.try_wait.parity.shared::cta.b64 pk, [t], ph; @pk bra START; add.u32 %128, %128, 1; setp.le.u32 pk, %128, %139; @pk bra FIRST; START:\n"
__device__ __forceinline__ void gemm1(float (&d)[128], Ring& r, uint64_t ha, uint64_t hb, int wg) {
    asm volatile(STEP_REGS "mul.lo.u32 k, %134, 15; mov.b32 ph, %134; setp.ne.u32 pl, k, 0; mad.lo.u32 t, %134, 8, %131;\n"
                 "pmevent 1; @pl bar.sync 1, 256;\n" FIRST_WAIT "@pl bra ONE;\n"
                 "LOOP: setp.ne.u32 pa, k, 0; and.pred pr, pa, ps; setp.eq.u32 pl, k, 15;\n"
                 STEP(0, 4, 1, ph, pa, pr, "@pl bar.arrive 1, 256;\n", "@pl bra END;\n")
                 "ONE: setp.ne.u32 pa, k, 15; and.pred pr, pa, ps; setp.eq.u32 pl, k, 30;\n"
                 STEP(1, 0, 2, ph, pa, pr, "@pl bar.arrive 2, 256;\n", "@pl bra END;\n")
                 STEP(2, 1, 3, ph, 1, ps, "", "") STEP(3, 2, 4, ph, 1, ps, "", "") "xor.b32 ph, ph, 1; add.u32 k, k, 5;\n" STEP(4, 3, 0, ph, 1, ps, "", "")
                 "bra LOOP;\n"
                 "END:\n" P4B "}" STEP_ARGS(0));
}
__device__ __forceinline__ void gemm2(float (&d)[128], Ring& r, uint64_t ha, uint64_t hb, int wg) {
    asm volatile(STEP_REGS "mov.b32 k, 0; mov.b32 ph, 0; add.u32 t, %131, 16;\n"
                 "pmevent 1; bar.sync 2, 256;\n" FIRST_WAIT
                 "LOOP: setp.ne.u32 pa, k, 0; and.pred pr, pa, ps; setp.eq.u32 pl, k, 5;\n"
                 STEP(2, 1, 3, ph, pa, pr, "", "") STEP(3, 2, 4, ph, 1, ps, "", "") "xor.b32 ph, ph, 1; add.u32 k, k, 1;\n" STEP(4, 3, 0, ph, 1, ps, "", "")
                 "@pl bra END;\n" STEP(0, 4, 1, ph, 1, ps, "", "") STEP(1, 0, 2, ph, 1, ps, "", "")
                 "bra LOOP;\n"
                 "END: }" STEP_ARGS(1));
}
template <int O, int K, int J> __device__ __forceinline__ void mma_h(float (&y)[128], uint64_t a, uint64_t b) { mma128_ss<O, 1, 0>(y, a + SL(K) * 2048 + O * 8 + 128 * J, b + SL(K) * 2048 + 2 * J, 1); }
template <int O, int K> __device__ __forceinline__ void half_step(float (&y)[128], uint64_t a, uint64_t b) { mma_h<O, K, 0>(y, a, b); mma_h<O, K, 1>(y, a, b); mma_h<O, K, 2>(y, a, b); mma_h<O, K, 3>(y, a, b); }
template <int R, int U> __device__ __forceinline__ void out_piece(float (&y)[128], const uint32_t (&dd)[16], uint32_t x0, uint32_t x1, float* op) {
    const int i = 64 * (R >> 1) + 8 * U + 2 * (R & 1);
    asm("mul.rn.bf16x2 %0, %0, %1;" : "+r"(x0) : "r"(dd[2 * U]));
    asm("mul.rn.bf16x2 %0, %0, %1;" : "+r"(x1) : "r"(dd[2 * U + 1]));
    asm volatile("st.global.v4.f32 [%0], {%1,%2,%3,%4};" ::"l"(op + (32 * (R & 1) + 16 * (R >> 1)) * 2048 + 16 * U),
                 "f"(y[i] + __uint_as_float(x0 << 16)), "f"(y[i + 1] + __uint_as_float(x0 & 0xffff0000u)),
                 "f"(y[i + 4] + __uint_as_float(x1 << 16)), "f"(y[i + 5] + __uint_as_float(x1 & 0xffff0000u)) : "memory");
}
template <int R, int U0> __device__ __forceinline__ void load_x4(uint32_t (&xx)[8], uint32_t xa) {
#pragma unroll
    for (int u = 0; u < 4; u++)
        asm volatile("ld.shared.v2.b32 {%0,%1}, [%2];" : "=r"(xx[2 * u]), "=r"(xx[2 * u + 1]) : "r"((xa ^ (u << 5)) + (3 - R) * 8192 + U0 * 1024) : "memory");
}
__device__ __forceinline__ Ring ring_at(uint32_t sb, int k) {
    Ring r;
    r.n = 0;
    r.full = sb + OFF_BAR + B_FULL;
    asm("mapa.shared::cluster.u32 %0, %1, %2;" : "=r"(r.rel) : "r"(sb + OFF_BAR + B_EMPTY), "r"((threadIdx.x >> 5) & 1));
    r.sig = __shfl_sync(~0u, threadIdx.x & 95, threadIdx.x) == 0;
    return r;
}

template <bool BY_SM> __global__ void __cluster_dims__(2, 1, 1) __launch_bounds__(512, 1)
fused_kernel(const __grid_constant__ CUtensorMap tmX, const __grid_constant__ CUtensorMap tmBre, const __grid_constant__ CUtensorMap tmBim,
             const __grid_constant__ CUtensorMap tmCre, const __grid_constant__ CUtensorMap tmCim, const __grid_constant__ CUtensorMap tmXd,
             const __grid_constant__ CUtensorMap tmUst, const __grid_constant__ CUtensorMap tmVst,
             const __grid_constant__ CUtensorMap tmWr, const __grid_constant__ CUtensorMap tmWi, const __grid_constant__ CUtensorMap tmXa,
             const Params p) {
    extern __shared__ __align__(1024) uint8_t smraw[];
    asm volatile(".reg .pred pk, p0;");
    const int tid = threadIdx.x, rank = blockIdx.x & 1;
    const uint32_t wi = __shfl_sync(~0u, smem_u32(smraw) + (tid >> 5), 0), sb = wi & ~15u, bars = sb + OFF_BAR;
    const int wg = (wi >> 2) & 3, w = wi & 3, lane = tid & 31, g = lane >> 2, q = lane & 3;
    if (wg != 3) asm volatile("barrier.cluster.arrive.relaxed.aligned; barrier.cluster.wait.aligned;" ::: "memory");
    else asm volatile("prefetch.tensormap [%0];" ::"l"(w == 0 ? &tmX : w == 1 ? &tmBre : &tmBim) : "memory");
    int role;
    {
        uint32_t T = blockIdx.x;
        if (BY_SM) asm("mov.u32 %0, %%smid;" : "=r"(T));
        T >>= 1;
        const uint32_t a = ((T - 32) * 37) >> 8;
        asm("{.reg .pred p; setp.lt.u32 p, %1, 62; selp.u32 %0, 4, -58, p; add.u32 %0, %0, %1;\n"
            "setp.lt.u32 p, %1, 60; selp.u32 %0, %2, %0, p; setp.lt.u32 p, %1, 32; selp.u32 %0, %3, %0, p;}"
            : "=&r"(role) : "r"(T), "r"(8 * (T - 31 - 7 * a) + 4 + a), "r"(8 * (T & 7) + (T >> 3)));
        role = 2 * role + rank;
    }
    const bool spare = role >= 128;
    const int tc = ((role >> 3) & 14) + rank, cb = (role >> 1) & 7;
    const int fb = role >> 5, fcb = role & 31, fpos = pos_of(fcb);
    const int nu = role == 128 ? 1 : (fcb || !role ? 2 : 0);

    if (wg == 3) {
        if (elect_one()) {
            const uint32_t b = bars + w * 8;
            STAMP5(57);
            mbar_init(b, 1);
            if (w < 3 && !spare) {
                mbar_expect_tx(b, 32768);
                tma5d(sb + w * 32768 + 16384, &tmX, w * 64, 0, 0, 0, tc, b);
                if (w == 0) { tma4d(sb, &tmBre, 0, 0, 0, cb * 4, b); tma4d(sb + 8192, &tmBim, 0, 0, 0, cb * 4, b); }
                STAMP5(58);
            }
#pragma unroll
            for (int o = 32; o < B_EPOCH; o += 32) mbar_init(b + o, o < B_EMPTY ? 1 : (o < B_STG ? 2 : (o < B_P3M ? 4 : 8)));
            asm volatile("fence.mbarrier_init.release.cluster;" ::: "memory");
        }
        __syncwarp();
        STAMP5(59);
        asm volatile("barrier.cluster.arrive.relaxed.aligned;" ::: "memory");
    }
    if (opaque32(wg) == 3) {
        asm volatile("setmaxnreg.dec.sync.aligned.u32 24;");
        asm volatile("barrier.cluster.wait.aligned;" ::: "memory");
        if (w == 0) {
            if (!spare && elect_one()) {
                STAMP(56);
#pragma unroll 1
                for (int k = 1; k < NST; k++) {
                    if (k >= 3) mbar_expect_tx(bars + B_FULL + k * 8, 32768);
                    tma4d_mc(sb + k * 32768 + rank * 8192, rank ? &tmBim : &tmBre, k * 64, 0, 0, cb * 4, bars + B_FULL + k * 8);
                    if (k >= 3) tma5d(sb + k * 32768 + 16384, &tmX, k * 64, 0, 0, 0, tc, bars + B_FULL + k * 8);
                }
#define RING_WAIT "mbarrier.try_wait.parity.shared::cta.b64 p, [fb + 256], ph; @p bra GO;\n" \
                  "WAIT: mbarrier.try_wait.parity.shared::cta.b64 p, [fb + 256], ph; add.u32 n, n, 1; setp.gt.or.u32 p, n, 32768, p; @!p bra WAIT;\nGO:\n"
#define RING_NEXT "pmevent 1; add.u32 o, o, 8; setp.eq.u32 p, o, 40; selp.u32 o, 0, o, p; @p xor.b32 ph, ph, 1; add.u32 fb, %1, o; shl.b32 t, o, 12; add.u32 da, %0, t;\n"
                asm volatile("{.reg .b32 o, k, kk, c2, da, db, fb, ph, n, t; .reg .pred p;\n"
                             "mov.b32 o, 0; mov.b32 k, 320; mov.b32 kk, 320; mov.b32 c2, 0; mov.b32 ph, 0; mov.b32 n, 0; mov.b32 fb, %1; mov.b32 da, %0; mov.b32 db, %2;\n"
                             "LOOP:\n" RING_WAIT
                             "cp.async.bulk.tensor.5d.shared::cluster.global.mbarrier::complete_tx::bytes [da], [%3, {kk,0,0,0,%5}], [fb];\n"
                             "cp.async.bulk.tensor.4d.shared::cluster.global.mbarrier::complete_tx::bytes.multicast::cluster [db], [%4, {kk,0,c2,%6}], [fb], %7;\n"
                             "mbarrier.arrive.expect_tx.shared::cta.b64 _, [fb], 32768;\n" RING_NEXT
                             "add.u32 db, %2, t; add.u32 k, k, 64; and.b32 kk, k, 1023; shr.u32 c2, k, 9; and.b32 c2, c2, 2; setp.ne.u32 p, k, 2048; @p bra LOOP;}"
                             ::"r"(sb + 16384), "r"(bars + B_FULL), "r"(sb + rank * 8192), "l"(&tmX), "l"(rank ? &tmBim : &tmBre), "r"(tc), "r"(cb * 4), "h"((uint16_t)3) : "memory");
                asm volatile("{.reg .b32 o, k, kk, da, db, fb, hb, ph, n, t; .reg .b64 m, src; .reg .pred p;\n"
                             "mov.b32 o, 16; mov.b32 k, 0; mov.b32 kk, 0; mov.b32 ph, 1; mov.b32 n, 0; add.u32 fb, %1, 16; add.u32 hb, %1, 72; add.u32 da, %0, 65536; add.u32 db, %2, 65536;\n"
                             "mov.b64 m, %3; mov.b64 src, %5;\n"
                             "GROUP: add.u32 t, %8, k;\n"
                             "OWN: mbarrier.try_wait.parity.shared::cta.b64 p, [t], 0; add.u32 n, n, 1; setp.gt.or.u32 p, n, 32768, p; @!p bra OWN;\n"
                             "LOOP:\n" RING_WAIT
                             "cp.async.bulk.shared::cluster.global.mbarrier::complete_tx::bytes [da], [src], 16384, [hb];\n"
                             "cp.async.bulk.tensor.5d.shared::cluster.global.mbarrier::complete_tx::bytes.multicast::cluster [db], [m, {kk,0,0,0,%6}], [fb], %7;\n"
                             "mbarrier.expect_tx.shared::cta.b64 [fb], 16384; mbarrier.arrive.expect_tx.shared::cta.b64 _, [hb], 16384;\n" RING_NEXT
                             "add.u32 db, %2, t; add.u64 src, src, 16384; sub.u64 m, %4, m; add.u32 k, k, 1; shl.b32 kk, k, 5; and.b32 kk, kk, 0x7c0;\n"
                             "and.b32 t, k, 1; mad.lo.u32 hb, t, 8, fb; add.u32 hb, hb, o; add.u32 hb, hb, 40;\n"
                             "and.b32 t, k, 7; setp.ne.u32 p, t, 0; @p bra LOOP; setp.ne.u32 p, k, 32; @p bra GROUP;}"
                             ::"r"(sb), "r"(bars + B_FULL), "r"(sb + 16384 + rank * 8192), "l"(&tmCre), "l"((uint64_t)&tmCre + (uint64_t)&tmCim),
                               "l"(g_H + (size_t)tc * 32 * 16384), "r"(cb * 8 + rank * 4), "h"((uint16_t)3), "r"(bars + B_HOWN) : "memory");
            }
        } else if (opaque32(w) == 1) {
            const unsigned ep = ld_rlx(g_epoch + role * 8) + 1;
            __syncwarp();
            if (elect_one()) {
                asm volatile("st.relaxed.gpu.global.u32 [%0], %1;" ::"l"(g_epoch + role * 8), "r"(ep) : "memory");
                asm volatile("st.shared.u32 [%0], %1;" ::"r"(bars + B_EPOCH), "r"(ep) : "memory");
                mbar_arrive(bars + B_EP);
            }
            int slot;
            const int kap1 = unit_of(role, 1, slot);
            uint32_t lph = 0;
            if (!spare) mbar_wait(bars + B_STGU, 0);
            STAMP(21);
            const int c0 = fb * 2048 + fpos * 64;
            if (elect_one()) {
                if (!spare) {
#pragma unroll 1
                    for (int r = 4; r < 8; r++) bulk_st(g_X + r * (32 * 16384) + c0 * 2, sb + OFF_P + r * 4096, 128);
                    tma2d_st(&tmUst, c0, 0, sb + OFF_P);
                    bulk_commit();
                    tma2d_st(&tmUst, c0, 64, sb + OFF_P + 8192);
                    bulk_commit();
                    asm volatile("cp.async.bulk.wait_group.read 1;" ::: "memory");
                    red_hint(g_cnt);
                }
            }
            STAMP(40);
#pragma unroll 1
            for (int e = 0; e < 4; e++) {
                if (e >= 2) {
                    if (e == nu) {
                        mbar_wait(bars + B_WFREE, !spare);
                        load_w_rows(sb + OFF_WD, &tmWr, &tmWi, kap1, bars + B_WD);
                    }
                    if (e - 2 < nu) mbar_wait(bars + B_STG, e & 1);
                    STAMPO(23, e - 2);
                    if (e == nu && elect_one()) {
                        const int c = (role ? slot : 256) * 32;
                        tma2d_st(&tmVst, c, 0, sb + OFF_P);
                        tma2d_st(&tmVst, c + 4096, 0, sb + OFF_P + 8192);
                        bulk_commit();
                        if (role) { bulk_wait_read(); red_hint(g_cnt + 64); } else bulk_wait_all();
                    }
                    if (e == 3 && !spare && elect_one()) {
                        mbar_expect_tx(bars + B_FG, 8192);
                        bulk_ld(sb + OFF_F, (const uint8_t*)g_tab + TAB_G + fb * 8192, 8192, bars + B_FG);
                    }
                }
                const uint32_t tg = e < 2 ? lane * 128 + ((((lane >> 1) & 2) ^ (lane & 3)) << 4) + (lane >> 3) * 4 : lane * 64 + (lane & 8) * 4 + (lane & 2) * 8 + (lane & 4) * 2;
                if (spare) {
                    if (e == 1) {
                        wait_cnt(g_cnt, 128 * ep);
                        STAMP(42);
#pragma unroll 1
                        for (int n = 0; n < 4096; n++) {
                            if (elect_one()) {
                                mbar_expect_tx(bars + B_LD, 8 * 16384);
#pragma unroll 1
                                for (int r = 0; r < 8; r++) bulk_ld(sb + r * 16384, g_X + (size_t)r * (32 * 16384), 16384, bars + B_LD);
                            }
                            mbar_wait(bars + B_LD, n & 1);
                            bool ok = true;
#pragma unroll 1
                            for (int r = 0; r < 8; r++) ok &= tags_ok<4096>(sb + r * 16384 + tg, ep);
                            if (ok) break;
                        }
                        if (elect_one()) mbar_arrive(bars + B_RAW);
                    }
                } else {
                    const uint32_t dst = sb + OFF_P + (e & 1) * 16384;
#define X_ST1
#define X_ST2
#define X_RETRY
#define X_ARG
                    asm volatile("{.reg .b32 n, a, v0, v1, v2, v3; .reg .pred p, pe, pu, pm;\n"
                                 "elect.sync _|pe, 0xffffffff; setp.lt.u32 pu, %10, 2; sub.u32 a, %10, 1; setp.lt.u32 pm, a, 2; mov.b32 n, 0; pmevent 1;\n"
                                 "POLL: ld.relaxed.gpu.global.u32 v0, [%1]; setp.eq.u32 p, v0, %2; @p bra LOAD;\n"
                                 "nanosleep.u32 20; add.u32 n, n, 1; setp.lt.u32 p, n, 32768; @p bra POLL;\n"
                                 "LOAD:\n" X_ST1 "cp.async.bulk.wait_group.read 0;\n"
                                 "@pe cp.async.bulk.shared::cluster.global.mbarrier::complete_tx::bytes [%3], [%4], 8192, [%5]; @pe mbarrier.arrive.expect_tx.shared::cta.b64 _, [%5], 16384;\n"
                                 "@pm nanosleep.u32 400; @pe cp.async.bulk.shared::cluster.global.mbarrier::complete_tx::bytes [%3 + 8192], [%4 + 8192], 8192, [%5];\n"
                                 "mov.b32 a, 0;\n"
                                 "WAIT: mbarrier.try_wait.parity.shared::cta.b64 p, [%5], %0; @p bra CHECK; add.u32 n, n, 1; setp.lt.u32 p, n, 65536; @p bra WAIT;\n"
                                 "CHECK:\n" X_ST2 "@pu bra FOUR;\n"
                                 "ld.shared.u32 a, [%7]; ld.shared.u32 v0, [%6 + 2048]; ld.shared.u32 v1, [%6 + 6144]; ld.shared.u32 v2, [%6 + 10240]; ld.shared.u32 v3, [%6 + 14336];\n"
                                 "lop3.b32 a, a, v0, %8, 0x7e; lop3.b32 v1, v1, v2, %8, 0x7e; lop3.b32 a, a, v3, %8, 0xf6; or.b32 a, a, v1;\n"
                                 "FOUR: ld.shared.u32 v0, [%6]; ld.shared.u32 v1, [%6 + 4096]; ld.shared.u32 v2, [%6 + 8192]; ld.shared.u32 v3, [%6 + 12288];\n"
                                 "lop3.b32 a, a, v0, %8, 0xf6; lop3.b32 a, a, v1, %8, 0xf6; lop3.b32 v2, v2, v3, %8, 0x7e; lop3.b32 a, a, v2, 1, 0xa8;\n"
                                 "setp.eq.u32 p, a, 0; vote.sync.all.pred p, p, -1; @p bra OK;\n" X_RETRY
                                 "add.u32 n, n, 16; setp.ge.u32 p, n, 65536; @p bra OK; xor.b32 %0, %0, 1; bra LOAD;\n"
                                 "OK: @pe mbarrier.arrive.shared::cta.b64 _, [%9]; pmevent 1; xor.b32 %0, %0, 1;}"
                                 : "+r"(lph)
                                 : "l"(g_cnt + e * 32), "r"(128 * ep), "r"(dst), "l"(g_X + (size_t)(e < 2 ? role + e * 128 : 254 + (fb * 32 + fpos) * 2 + e) * 16384), "r"(bars + B_LD),
                                   "r"(dst + tg), "r"(dst + (e == 3 ? (lane & 1) * 8192 + 32 : 0)), "r"(ep), "r"(bars + B_IN + e * 8), "r"(e) X_ARG : "memory");
                }
                if (e == 0 && !spare && elect_one()) {
                    tma2d_st(&tmUst, c0, 128, sb + OFF_P + 16384);
                    tma2d_st(&tmUst, c0, 192, sb + OFF_P + 24576);
                    bulk_commit();
                    bulk_wait_read();
                    red_hint(g_cnt + 32);
                }
            }
            if (!spare) {
                mbar_wait(bars + B_HOWN + 8, 0);
#pragma unroll 1
                for (int r = 0; r < 4; r++) {
                    if (r == 3) mbar_wait(bars + B_P3M, 0);
                    if (elect_one()) {
                        if (r == 0) { mbar_expect_tx(bars + B_XD, 24576 + 256); mbar_expect_tx(bars + B_XD + 8, 8192); bulk_ld(sb + OFF_LAM, p.dsk + cb * 128, 256, bars + B_XD); }
                        tma4d(sb + OFF_F + (3 - r) * 8192, &tmXd, 0, tc * 128 + 32 * (r & 1) + 16 * (r >> 1), 0, cb * 2, bars + B_XD + (r == 3) * 8);
                    }
                    __nanosleep(PACE_X);
                }
            }
        } else {
            if (w == 2) {
                {
                    const int u = lane >> 4;
                    int slot;
                    const int r0 = unit_of(role, u, slot) + 512 * ((lane >> 1) & 3), r1 = (2048 - r0) & 2047, mir = (lane >> 3) & 1;
                    const unsigned short* wp = (const unsigned short*)((lane & 1) ? p.wi : p.wr);
                    const float a = bf2f(wp[r0 * 513 + mir * 512]), b = bf2f(wp[r1 * 513 + mir * 512]);
                    asm volatile("st.shared.f32 [%0], %1;" ::"r"(sb + OFF_WSP + u * 64 + (lane & 15) * 4), "f"(0.5f * ((lane & 1) ? (mir ? b - a : a - b) : a + b)) : "memory");
                }
                warp_arrive(bars + B_WSP);
                int slot;
                const int kap = unit_of(role, 0, slot);
                if (!spare) mbar_wait(bars + B_WFREE, 0);
                if (elect_one()) {
                    mbar_expect_tx(bars + B_FG, 8192);
                    bulk_ld(sb + OFF_F, (const uint8_t*)g_tab + TAB_FG, 8192, bars + B_FG);
                }
                if (nu) load_w_rows(sb + OFF_WD, &tmWr, &tmWi, kap, bars + B_WD);
            } else if (!spare) {
#pragma unroll 1
                for (int i = 0; i < 8; i++) {
                    if (i >= XA_N0) __nanosleep(XA_PACE);
                    if (elect_one()) {
                        const uint32_t xb = bars + (i < 4 ? B_RAW : B_XIN);
                        if (!(i & 3)) mbar_expect_tx(xb, 16384);
                        tma3d(sb + OFF_F + i * 4096, &tmXa, fcb * 32, 0, 4 * i + fb, xb);
                    }
                }
            }
            if (!spare) {
                const unsigned ep = get_epoch(bars);
#define CNT_RETRY
#define CNT_ARG
                asm volatile("{.reg .b32 o, k, hb, fb, ca, m, ph, rph, n, t, v0, v1, v2, v3; .reg .b64 src; .reg .pred p, pe;\n"
                             "elect.sync _|pe, 0xffffffff; mov.b32 o, %0; shr.u32 k, %0, 3; sub.u32 k, k, 2; mov.b32 m, 0x107c0; mov.b32 rph, 0; mov.b32 n, 0;\n"
                             "bra NEXT;\n"
                             "LOOP: mbarrier.try_wait.parity.shared::cta.b64 p, [hb], ph; @p bra GO;\n"
                             "WAIT: mbarrier.try_wait.parity.shared::cta.b64 p, [hb], ph; add.u32 n, n, 1; setp.gt.or.u32 p, n, 32768, p; @!p bra WAIT;\n"
                             "GO: ld.shared.u32 v0, [ca]; ld.shared.u32 v1, [ca + 128]; ld.shared.u32 v2, [ca + 256]; ld.shared.u32 v3, [ca + 384];\n"
                             "lop3.b32 v0, v0, v1, %4, 0x7e; lop3.b32 v2, v2, v3, %4, 0x7e; lop3.b32 v0, v0, v2, 1, 0xa8; setp.eq.u32 p, v0, 0; vote.sync.all.pred p, p, -1; @p bra OK;\n"
                             CNT_RETRY "add.u32 n, n, 16; setp.gt.u32 p, n, 32768; @p bra OK;\n"
                             "shl.b32 t, o, 12; add.u32 t, t, %5; mad.wide.u32 src, k, 16384, %6;\n"
                             "@pe mbarrier.arrive.expect_tx.shared::cta.b64 _, [%7], 16384; @pe cp.async.bulk.shared::cluster.global.mbarrier::complete_tx::bytes [t], [src], 16384, [%7];\n"
                             "AGAIN: mbarrier.try_wait.parity.shared::cta.b64 p, [%7], rph; add.u32 n, n, 1; setp.gt.or.u32 p, n, 32768, p; @!p bra AGAIN;\n"
                             "xor.b32 rph, rph, 1; bra GO;\n"
                             "OK: @pe mbarrier.arrive.shared::cta.b64 _, [fb]; pmevent 1;\n"
                             "add.u32 o, o, 16; setp.ge.u32 p, o, 40; @p sub.u32 o, o, 40; add.u32 k, k, 2;\n"
                             "NEXT: shr.u32 m, m, 1; and.b32 ph, m, 1; add.u32 fb, %1, o; mad.lo.u32 hb, o, 2, %2; mad.lo.u32 ca, o, 4096, %3; setp.lt.u32 p, k, 32; @p bra LOOP;}"
                             ::"r"(8 * w), "r"(bars + B_FULL), "r"(bars + B_HL - 16 + w * 8), "r"(sb + (q >> 1) * 8192 + (q & 1) * 512 + g * 1040 + q * 4), "r"(ep),
                               "r"(sb), "l"(g_H + (size_t)tc * 32 * 16384), "r"(bars + B_HR - 16 + w * 8) CNT_ARG : "memory");
                if (w == 3) warp_arrive(bars + B_DONE);
            }
        }
    } else {
        STAMP(55);
        asm volatile("setmaxnreg.inc.sync.aligned.u32 152;");
        STAMP5(60);
        const int t7 = tid & 127, hf = wg - 1;
        const int mi = lane >> 3, gl = lane & 7;
        if (spare && wg != 2) {
            if (tid < 64) { const uint4 v = __ldg((const uint4*)((const uint8_t*)g_tab + TAB_PC) + tid); sts128(sb + OFF_LAM + tid * 16, v.x, v.y, v.z, v.w); }
            bar_sync(1, 256);
            mbar_wait(bars + B_RAW, 0);
            STAMP(0);
#pragma unroll 1
            for (int u = 0; u < nu; u++) {
                int slot;
                const int t = unit_of(role, u, slot) >> 5;
                const uint32_t off = (tid >> 2) * 128 + q * 16;
                float zr[16], zi[16];
#pragma unroll
                for (int k = 0; k < 16; k++) zr[k] = zi[k] = 0.f;
#pragma unroll 1
                for (int r = (t & 1) ? 0 : t >> 1; r < 8 - ((t & 1) ? 0 : (t >> 1) - 1); r += (t & 1) ? 1 : 8 - t) {
                    float4 c;
                    float a[8], b[8];
                    lds128f(sb + OFF_LAM + t * 128 + r * 16, c.x, c.y, c.z, c.w);
                    lds128f(sb + r * 16384 + off, a[0], a[1], a[2], a[3]);
                    lds128f(sb + r * 16384 + off + 64, b[0], b[1], b[2], b[3]);
                    lds128f(sb + r * 16384 + off + 8192, a[4], a[5], a[6], a[7]);
                    lds128f(sb + r * 16384 + off + 8192 + 64, b[4], b[5], b[6], b[7]);
#pragma unroll
                    for (int k = 0; k < 16; k++) {
                        const uint32_t ua = __float_as_uint(a[k >> 1]), ub = __float_as_uint(b[k >> 1]);
                        const float x = __uint_as_float((k & 1) ? ua & 0xffff0000u : ua << 16), y = __uint_as_float((k & 1) ? ub & 0xffff0000u : ub << 16);
                        zr[k] = fmaf(c.x, x, fmaf(c.z, y, zr[k]));
                        zi[k] = fmaf(c.y, x, fmaf(c.w, y, zi[k]));
                    }
                }
                const uint32_t dst = sb + OFF_P + u * 16384 + off;
#pragma unroll
                for (int k = 0; k < 16; k += 8) {
                    sts128(dst + k * 1024, pk(zr[k], zr[k + 1]), pk(zr[k + 2], zr[k + 3]), pk(zr[k + 4], zr[k + 5]), pk(zr[k + 6], zr[k + 7]));
                    sts128(dst + k * 1024 + 64, pk(zi[k], zi[k + 1]), pk(zi[k + 2], zi[k + 3]), pk(zi[k + 4], zi[k + 5]), pk(zi[k + 6], zi[k + 7]));
                }
                fence_async_sm();
                bar_sync(1, 256);
                if (tid == 0) mbar_arrive(bars + B_IN + u * 8);
                STAMPO(1, u);
            }
            return;
        }
        if (wg == 2 && !spare) {
            asm volatile("setmaxnreg.inc.sync.aligned.u32 176;");
            uint32_t f1[16];
            cf tw[8];
            if (TAB_T0) __nanosleep(TAB_T0);
            ldtab<4, 2048>(f1, TAB_F1 + t7 * 16);
            ldtab_cf<16>(tw, TAB_TW1 + (t7 >> 2) * 64);
            const uint32_t ep = get_epoch(bars);
            uint32_t a0 = sb + OFF_P + (8 * w + gl + 32 * (mi >> 1)) * 128 + (((((mi & 1) << 2) | (fpos & 3)) ^ gl) << 4);
            float acc[128];
            const uint64_t dx = opaque(mkdesc(sb + OFF_F, 4096, 512, 2));
            mbar_wait(bars + B_RAW, 0);
            pinu(f1);
            wg_fence();
#pragma unroll
            for (int j = 0; j < 4; j++) mma128_rs<0, 1>(acc, f1[4 * j], f1[4 * j + 1], f1[4 * j + 2], f1[4 * j + 3], dx + j * 64, j);
            wg_commit();
            mbar_wait(bars + B_XIN, 0);
            wg_fence();
            STAMP(20);
#pragma unroll
            for (int j = 0; j < 4; j++) mma128_rs<64, 1>(acc, f1[4 * j], f1[4 * j + 1], f1[4 * j + 2], f1[4 * j + 3], dx + 1024 + j * 64, j);
            wg_commit();
            wg_wait<0>();
            pin(acc);
            pinu(f1);
            warp_arrive(bars + B_WFREE);
#pragma unroll 1
            for (int h = 0;; h++) {
                const uint32_t tmask = 2 * q + h == fpos >> 2 ? ~1u : ~0u, tbit = ep & ~tmask;
#pragma unroll
                for (int cl = 0; cl < 2; cl++) {
                    c2 v[8];
#pragma unroll
                    for (int n = 0; n < 8; n++) {
                        const int i = 4 * (4 * n + cl);
                        v[n] = {{acc[i], acc[i + 2]}, {acc[i + 1], acc[i + 3]}};
                    }
                    dft8<true, YP1>(v, tw);
#pragma unroll
                    for (int r = 0; r < 8; r += 2) {
                        uint32_t o0 = pk(v[r].a.x, v[r].b.x), o1 = pk(v[r].a.y, v[r].b.y), o2 = pk(v[r + 1].a.x, v[r + 1].b.x), o3 = pk(v[r + 1].a.y, v[r + 1].b.y);
                        if (cl == 0) { o0 = (o0 & tmask) | tbit; o2 = (o2 & tmask) | tbit; }
                        stsm4((a0 ^ (cl << 4)) + r * 4096, o0, o1, o2, o3);
                    }
                }
                if (h) break;
                a0 ^= 32;
#pragma unroll
                for (int n = 0; n < 8; n++) {
                    asm volatile("mov.b32 %0, %8; mov.b32 %1, %9; mov.b32 %2, %10; mov.b32 %3, %11; mov.b32 %4, %12; mov.b32 %5, %13; mov.b32 %6, %14; mov.b32 %7, %15; pmevent 1;"
                                 : "=&f"(acc[16 * n]), "=&f"(acc[16 * n + 1]), "=&f"(acc[16 * n + 2]), "=&f"(acc[16 * n + 3]), "=&f"(acc[16 * n + 4]), "=&f"(acc[16 * n + 5]), "=&f"(acc[16 * n + 6]), "=&f"(acc[16 * n + 7])
                                 : "f"(acc[16 * n + 8]), "f"(acc[16 * n + 9]), "f"(acc[16 * n + 10]), "f"(acc[16 * n + 11]), "f"(acc[16 * n + 12]), "f"(acc[16 * n + 13]), "f"(acc[16 * n + 14]), "f"(acc[16 * n + 15]));
                }
            }
            fence_async_sm();
            warp_arrive(bars + B_STGU);
            bar_sync(3, 128);
            asm volatile("setmaxnreg.dec.sync.aligned.u32 152;");
            bar_arrive(7, 256);
        }
        if (wg == 1) {
            if (LAM_T0) __nanosleep(LAM_T0);
            const int cl = tid & 127, ch = (cl >> 6) * 512 + ((cl >> 3) & 1) * 256 + cb * 32 + ((cl >> 4) & 3) * 8 + (cl & 7);
            const float lr = bf2f(*(const unsigned short*)padd(p.lre, 2 * ch)), li = bf2f(*(const unsigned short*)padd(p.lim, 2 * ch));
            const float dt = __bfloat162float(__float2bfloat16(expf(bf2f(*(const unsigned short*)padd(p.ldt, 2 * ch)))));
            const float an = dt * li, th = an * 0.318309873342514f;
            float sn, cs, inv;
            sincospif(fmaf(rintf(0.5f * th), -2.f, th) + fmaf(an, 1.2841276653e-8f, fmaf(an, 0.318309873342514f, -th)), &sn, &cs);
            const float ex = expf(dt * lr), br = ex * cs, bi = ex * sn;
            asm("rcp.approx.f32 %0, %1;" : "=f"(inv) : "f"(lr * lr + li * li));
            inv += inv;
            const float cr = ((br - 1.f) * lr + bi * li) * inv, ci = (bi * lr - (br - 1.f) * li) * inv;
            sts128(sb + OFF_LAM + cl * 16, __float_as_uint(br), __float_as_uint(-bi), __float_as_uint(cr), __float_as_uint(-ci));
            mbar_wait(bars + B_EP, 0);
            bar_sync(8, 128);
            if (tid == 128) mbar_arrive(bars + B_LAM);
        }
        if (wg != 2) {
        if (wg == 0) bar_sync(4, 128); else bar_sync(7, 256);
        asm volatile("setmaxnreg.inc.sync.aligned.u32 160;");
        if (wg == 0) bar_sync(4, 128);
        float d[128];
        STAMPW(0, 10);
        Ring rg = ring_at(sb, role * 66 + wg * 16);
        cf lam[2];
        unsigned ep;
        gemm1(d, rg, ring_desc(sb, 0, 16, 1), ring_desc(sb, 16384, 16, 1), wg);
        const uint32_t lama = sb + OFF_LAM + wg * 1024 + w * 256 + (fresh_lane() & 28) * 4;
        mbar_wait(bars + B_LAM, 0);
        lam[0] = lds_cf(lama); lam[1] = lds_cf(lama + 128);
        asm volatile("ld.shared.u32 %0, [%1];" : "=r"(ep) : "r"(bars + B_EPOCH) : "memory");
        asm volatile("setmaxnreg.inc.sync.aligned.u32 176;");
        cf L[2] = {lam[0], lam[1]};
#pragma unroll
        for (int i = 0; i < 4; i++) { L[0] = csq(L[0]); L[1] = csq(L[1]); }
        asm volatile("" : "+f"(L[0].x), "+f"(L[0].y), "+f"(L[1].x), "+f"(L[1].y)::"memory");
        wg_wait<0>();
        ring_release(rg, 8 * wg);
        pin(d);
        STAMPW(1, 11);
        {
            const int lane = fresh_lane(), g = lane >> 2, q = lane & 3, mi = lane >> 3, gl = lane & 7;
            cf f[2], fb2[2];
#pragma unroll
            for (int i = 0; i < 17; i++) {
#pragma unroll
                for (int h = 0; h < 2; h++) {
                    const int r = 4 * (i >> 1) + 2 * h + (i & 1), r2 = 32 + 4 * ((i - 1) >> 1) + 2 * h + ((i - 1) & 1);
                    if (i < 16) f[h] = i ? cfma(lam[h], f[h], {d[r], -d[64 + r]}) : cf{d[r], -d[64 + r]};
                    if (i > 0) fb2[h] = i > 1 ? cfma(lam[h], fb2[h], {d[r2], -d[64 + r2]}) : cf{d[r2], -d[64 + r2]};
                    if (i && (h || !(YS & 8))) YIELD_S1();
                }
            }
            const uint8_t* cbase = (const uint8_t*)g_carry + (tc * 16 + wg * 8 + cb) * 512 + w * 64;
            const uint8_t* cptr = padd(cbase, g * 8);
            const unsigned tag = ep & 15u;
#pragma unroll
            for (int h = 0; h < 2; h++) { f[h] = cfma(L[h], f[h], fb2[h]); L[h] = csq(L[h]); }
            cf s0[2], s1[2], s2[2];
#pragma unroll
            for (int h = 0; h < 2; h++) {
                s0[h] = {__shfl_sync(~0u, f[h].x, 0, 4), __shfl_sync(~0u, f[h].y, 0, 4)};
                s1[h] = {__shfl_sync(~0u, f[h].x, 1, 4), __shfl_sync(~0u, f[h].y, 1, 4)};
                s2[h] = {__shfl_sync(~0u, f[h].x, 2, 4), __shfl_sync(~0u, f[h].y, 2, 4)};
            }
#pragma unroll
            for (int h = 0; h < 2; h++) {
                s1[h] = cfma(L[h], s0[h], s1[h]);
                s2[h] = cfma(L[h], s1[h], s2[h]);
                f[h] = cfma(L[h], s2[h], f[h]);
                asm volatile("{.reg .pred p; .reg .b64 a; setp.eq.u32 p, %3, 3; mov.b64 a, {%1,%2}; @p st.relaxed.gpu.global.b64 [%0], a;}" ::"l"(cptr + h * 256),
                             "r"((__float_as_uint(f[h].x) & ~15u) | tag), "f"(f[h].y), "r"(q) : "memory");
            }
            STAMPX(2, 12);
            cf gam = lds_cf(lama + 8);
            cf st = csel(q & 2, csel(q & 1, s2[0], s1[0]), csel(q & 1, s0[0], {0.f, 0.f}));
            const cf st1 = csel(q & 2, csel(q & 1, s2[1], s1[1]), csel(q & 1, s0[1], {0.f, 0.f}));
            cptr = padd(cbase - 4 * 8192, (3 - mi) * 8192 + gl * 8);
            const int nprev = tc - 1 - mi;
            const uint8_t* hptr = padd(g_H + (size_t)(tc * 32 + wg * 16 + (cb & 6)) * 16384 + ((cb & 1) * 4 + w) * 1024, g * 64 + ((q ^ (g >> 1)) << 4));
            const uint32_t hm = 4 * (g & 1) + (q ^ (g >> 1)) == (cb & 1) * 4 + w ? ~1u : ~0u;
            float u[64];
            uint64_t fv[4] = {tag, tag, tag, tag};
            prescale<0>(u, d, gam);
            gather(fv, cptr, nprev);
#pragma unroll 1
            for (int h = 0;; h++) {
                const cf L2 = csq(L[0]), M = csq(L2);
                cf M4 = csq(csq(M));
                M4 = {__shfl_sync(~0u, M4.x, 4 * gl), __shfl_sync(~0u, M4.y, 4 * gl)};
                cf lq = cmul(gam, cmul(csel(q & 1, L[0], {1.f, 0.f}), csel(q & 2, L2, {1.f, 0.f})));
                st = cmul(gam, st);
                asm volatile("pmevent 1;" : "+f"(lq.x), "+f"(lq.y), "+f"(st.x), "+f"(st.y));
#pragma unroll 1
                for (unsigned n = 0; __any_sync(~0u, (((uint32_t)fv[0] ^ tag) | ((uint32_t)fv[1] ^ tag) | ((uint32_t)fv[2] ^ tag) | ((uint32_t)fv[3] ^ tag)) & 15u) && n < SPIN_LIMIT; n++) gather(fv, cptr, nprev);
                if (!h) STAMPX(53, 54);
                cf P = as_cf(fv[3]), pj[4];
#pragma unroll
                for (int a = 2; a >= 0; a--) P = cfma(M4, P, as_cf(fv[a]));
                cptr += 256;
                asm volatile("" : "+f"(P.x), "+f"(P.y)::"memory");
                gather(fv, cptr, h ? -1 : nprev);
#pragma unroll
                for (int j = 3; j >= 0; j--) pj[j] = {__shfl_sync(~0u, P.x, g + 8 * j), __shfl_sync(~0u, P.y, g + 8 * j)};
                st = cfma(lq, cfma(M, cfma(M, cfma(M, pj[3], pj[2]), pj[1]), pj[0]), st);
                if (!h) STAMPX(3, 13);
                uint32_t keep = sb >> 28;
                scan2(u, lam[0], st, hptr, hm, ep & ~hm, keep);
                warp_arrive(bars + B_HOWN + wg * 16 + h * 8 + keep);
                if (h) break;
                STAMPW(4, 14);
                if (wg == 1 && nu) bar_sync(9, 256);
                lds128f(lama + 128, lam[0].x, lam[0].y, gam.x, gam.y);
                st = st1;
                L[0] = L[1];
                hptr += 8 * 16384;
                prescale<1>(u, d, gam);
            }
            STAMPW(5, 15);
        }
        if (wg == 0) bar_sync(4, 128); else bar_sync(8, 128);
        if (wg == 0) {
            asm volatile("setmaxnreg.dec.sync.aligned.u32 160;");
            float y[128];
            rg = ring_at(sb, role * 66 + 32);
            STAMP(6);
            STAMP(7);
            const uint64_t dA = ring_desc(sb, 0, 512, 2), dB = ring_desc(sb, 16384, 16, 1);
            gemm2(y, rg, dA, dB, 0);
            asm volatile("setmaxnreg.inc.sync.aligned.u32 184;");
            const int lane = fresh_lane(), g = lane >> 2, q = lane & 3;
            const int pg = 2 * (g & 3) + (g >> 2);
            float* op = (float*)padd(p.out + (size_t)(tc * 128 + 64 * (w & 1) + 8 * (w >> 1)) * 2048 + 1024 + cb * 128, pg * 8192 + q * 16);
            const uint32_t xa = sb + OFF_F + (16 * (w & 1) + 8 * (w >> 1) + pg) * 128 + (((q >> 1) ^ pg) << 4) + (q & 1) * 8;
#define HALF0(k) wg_fence(); peek(k < 63 ? rg.full + SL(k + 1) * 8 : bars + B_XD, PH(k + 1)); half_step<0, k>(y, dA, dB); wg_commit(); peek_wait(k < 63 ? rg.full + SL(k + 1) * 8 : bars + B_XD, PH(k + 1), rg.n);
            HALF0(60) HALF0(61) HALF0(62) HALF0(63)
            const uint64_t dB2 = ring_desc(sb >> 1, 16384, 16, 1);
            uint32_t xa0[8], xa1[8], dd[16];
#pragma unroll
            for (int i = 0; i < 8; i++) asm volatile("ld.shared.v2.b32 {%0,%1}, [%2];" : "=r"(dd[2 * i]), "=r"(dd[2 * i + 1]) : "r"(sb + OFF_LAM + q * 8 + 32 * i) : "memory");
            load_x4<0, 0>(xa0, xa);
            wg_fence();
            half_step<64, 64 - SKEW>(y, dA, dB2);
            wg_commit();
            wg_wait<1>();
#pragma unroll
            for (int i = 0; i < 64; i++) asm volatile("" : "+f"(y[i])::"memory");
            STAMP(16);
#define MM(n) if (4 + (n) < 4 * SKEW) { wg_fence(); mma_h<64, 65 - SKEW + (n) / 4, (n) % 4>(y, dA, dB2); mma_h<64, 65 - SKEW + (n) / 4, (n) % 4 + 1>(y, dA, dB2); }
#define OUT4(R, U, X, n) out_piece<R, U>(y, dd, X[0], X[1], op); MM(n) out_piece<R, U + 1>(y, dd, X[2], X[3], op); MM(n + 2) \
                         out_piece<R, U + 2>(y, dd, X[4], X[5], op); MM(n + 4) out_piece<R, U + 3>(y, dd, X[6], X[7], op); MM(n + 6)
            load_x4<0, 4>(xa1, xa);
            OUT4(0, 0, xa0, 0)
            load_x4<1, 0>(xa0, xa);
            OUT4(0, 4, xa1, 8)
            wg_commit();
            load_x4<1, 4>(xa1, xa);
            OUT4(1, 0, xa0, 16)
            load_x4<2, 0>(xa0, xa);
            OUT4(1, 4, xa1, 16)
            STAMP(18);
            wg_wait<0>();
#pragma unroll
            for (int i = 64; i < 128; i++) asm volatile("" : "+f"(y[i])::"memory");
            STAMP(8);
            load_x4<2, 4>(xa1, xa);
            mbar_wait(bars + B_XD + 8, 0);
            OUT4(2, 0, xa0, 16)
            load_x4<3, 0>(xa0, xa);
            OUT4(2, 4, xa1, 16)
            load_x4<3, 4>(xa1, xa);
            OUT4(3, 0, xa0, 16)
            OUT4(3, 4, xa1, 16)
            STAMP(9);
            return;
        }
        asm volatile("setmaxnreg.dec.sync.aligned.u32 152;");
        } else {
        if (nu) {
            cf T[8];
            const uint32_t ep = get_epoch(bars);
            const int ka = pos_of(t7 >> 2);
            {
                const cf s8 = twid(8 * ka, 1024);
                T[0] = twid(2 * q * ka, 1024);
                T[1] = twid((2 * q + 1) * ka, 1024);
#pragma unroll
                for (int i = 2; i < 8; i++) T[i] = cmul(T[i - 2], s8);
#pragma unroll
                for (int i = 0; i < 8; i += 2) asm volatile("pmevent 1;" : "+f"(T[i].x), "+f"(T[i].y), "+f"(T[i + 1].x), "+f"(T[i + 1].y));
            }
            asm volatile("setp.eq.u32 p0, %0, 0;" ::"r"(__shfl_sync(~0u, t7, lane)));
            mbar_wait(bars + B_WSP, 0);
            mbar_wait(bars + B_FG, 0);
            uint32_t wd[4], wm[4], vo[32];
            const uint8_t* vp;
            int slot;
            const int kap0 = unit_of(role, 0, slot), al = 2 * kap0;
            const int kap1 = __shfl_sync(~0u, unit_of(role, 1, slot), 0);
            slot = __shfl_sync(~0u, slot, 0);
            cf be1 = twid(kap0 + 512 * q, 2048), be2 = csq(be1), be3 = cmul(be1, be2);
#pragma unroll
            for (int j = 0; j < 4; j++) {
                wd[j] = sb + OFF_WD + ((j + q) & 3) * WPITCH + (al & 15) + 2 * ka + 64 * q;
                wm[j] = sb + OFF_WM + (((role ? 3 : 4) - j - q) & 3) * WPITCH + (-al & 15) + 1024 - 2 * ka - 64 * q;
                wd[j] = __shfl_sync(~0u, wd[j], lane);
            }
#pragma unroll 1
            for (int u = 0; u < nu; u++) {
                const uint32_t buf = sb + OFF_P + u * 16384;
                float acc[64], za[32], zb[32], ya[32], yb[32], vv[64];
                const uint64_t dF = opaque(mkdesc(sb + OFF_F, 16, 1024, 1)), dB = opaque(mkdesc(buf, 4096, 512, 2));
                mbar_wait(bars + B_IN + u * 8, 0);
                if (!role) {
                    const uint32_t z = buf + w * 1024 + (fresh_lane() >> 2) * 128 + 64 + (fresh_lane() & 3) * 16;
#pragma unroll
                    for (int i = 0; i < 4; i++) sts128(z + i * 4096, 0, 0, 0, 0);
                    fence_async_sm();
                    bar_sync(3, 128);
                }
                STAMP3(22);
                wg_fence();
#pragma unroll
                for (int j = 0; j < 4; j++) mma128_ss<0, 0, 1>(acc, dF + j * 2, dB + j * 64, j);
                wg_commit();
                if (u) {
                    const uint32_t va = sb + OFF_P + ((uint32_t)(vp - g_X) >> 9 & 0x7c0) + ((uint32_t)(uintptr_t)vp & 31) + (fresh_lane() & 4) * 8;
                    bar_sync(3, 128);
#pragma unroll
                    for (int k = 0; k < 16; k++) sts64(va + ((k >> 1) & 1) * 8192 + (k >> 2) * 2048 + (k & 1) * 256, vo[2 * k], vo[2 * k + 1]);
                    fence_async_sm();
                    warp_arrive(bars + B_STG);
                    if (!role) { const uint32_t t = wm[0]; wm[0] = wm[1]; wm[1] = wm[2]; wm[2] = wm[3]; wm[3] = t; }
                }
                STAMP3(39);
                wg_wait<0>();
                pin(acc);
                STAMP3(30);
                uint32_t af[16], ag[16];
#pragma unroll
                for (int k = 0; k < 8; k++) {
                    uint32_t(&o)[16] = k < 4 ? af : ag;
                    const int c = k & 3;
#pragma unroll
                    for (int b = 0; b < 2; b++) {
                        const int i = 4 * (4 * ((k >> 2) * 2 + b) + c);
                        c2 x = mul2(c2{{acc[i], acc[i + 2]}, {acc[i + 1], acc[i + 3]}}, c2{T[2 * c], T[2 * c + 1]});
                        o[4 * c + b] = pk(x.a.x, x.a.y);
                        o[4 * c + 2 + b] = pk(x.b.x, x.b.y);
                    }
                    asm volatile("" : "+r"(o[4 * c]), "+r"(o[4 * c + 1]), "+r"(o[4 * c + 2]), "+r"(o[4 * c + 3])::"memory");
                    wg_fence();
                    mma64_rs<0>(k < 4 ? za : zb, o[4 * c], o[4 * c + 1], o[4 * c + 2], o[4 * c + 3], dF + c * 2, c);
                }
                wg_commit();
                STAMP3(31);
                mbar_wait(bars + B_WD, u & 1);
                STAMP3(37);
                uint32_t wr[16];
#pragma unroll
                for (int i = 0; i < 16; i++) wr[i] = lds16(wd[i >> 2] + 256 * ((i >> 1) & 1) + (i & 1) * 4 * WPITCH);
                wg_wait<0>();
                pin(za);
                pin(zb);
                pinu(af);
                pinu(ag);
                STAMP3(32);
#pragma unroll
                for (int jb = 0; jb < 4; jb++) {
                    const int i = 8 * jb;
                    c2 s0 = {{za[i], za[i + 4]}, {za[i + 1], za[i + 5]}}, s2 = {{za[i + 2], za[i + 6]}, {za[i + 3], za[i + 7]}};
                    c2 s1 = {{zb[i], zb[i + 4]}, {zb[i + 1], zb[i + 5]}}, s3 = {{zb[i + 2], zb[i + 6]}, {zb[i + 3], zb[i + 7]}};
                    c2 W[4];
                    auto wcvt = [&](int j) {
                        asm volatile("shl.b32 %0, %4, 16; shl.b32 %1, %5, 16; shl.b32 %2, %6, 16; shl.b32 %3, %7, 16;"
                                     : "=&f"(W[j].a.x), "=&f"(W[j].a.y), "=&f"(W[j].b.x), "=&f"(W[j].b.y) : "r"(wr[4 * j]), "r"(wr[4 * j + 1]), "r"(wr[4 * j + 2]), "r"(wr[4 * j + 3]));
                        if ((jb & 1) == 0)
                            asm volatile("@p0 ld.shared.v2.f32 {%0,%1}, [%2];" : "+f"(W[j].a.x), "+f"(W[j].a.y) : "r"(sb + OFF_WSP + u * 64 + jb * 16 + j * 8));
                        if (jb < 3) {
#pragma unroll
                            for (int k = 4 * j; k < 4 * j + 4; k++) {
                                const int e = (k >> 1) & 1, pl = (k & 1) * 4 * WPITCH;
                                wr[k] = jb == 0 ? lds16(wd[j] + 512 + 256 * e + pl) : lds16(wm[j] - 512 * (jb - 1) - 256 * e + pl);
                            }
                        }
                        if (jb >= 2) { W[j].a.y = -W[j].a.y; W[j].b.y = -W[j].b.y; }
                    };
                    wcvt(0);
                    s2 = mul2(s2, be1);
                    s1 = fma2(s1, be2, s0);
                    wcvt(1);
                    s3 = fma2(s3, be3, s2);
                    { const c2 x = twm2(s0, s1), y = twm2(s2, s3); s0 = s1; s2 = s3; s1 = x; s3 = y; }
                    wcvt(2);
                    bfly<0>(s0, s2); bfly_mi<0>(s1, s3);
                    wcvt(3);
                    s0 = mul2(s0, W[0]); s1 = mul2(s1, W[1]);
                    bfly_tw<0>(s0, s2, W[2], s1, s3, W[3]);
                    bfly<0>(s0, s1); bfly_mi<0>(s2, s3);
                    af[4 * jb] = pk(s0.a.x, s0.b.x); af[4 * jb + 1] = pk(s3.a.x, s3.b.x); af[4 * jb + 2] = pk(s0.a.y, s0.b.y); af[4 * jb + 3] = pk(s3.a.y, s3.b.y);
                    ag[4 * jb] = pk(s1.a.x, s1.b.x); ag[4 * jb + 1] = pk(s2.a.x, s2.b.x); ag[4 * jb + 2] = pk(s1.a.y, s1.b.y); ag[4 * jb + 3] = pk(s2.a.y, s2.b.y);
                }
                pinu(af);
                pinu(ag);
                warp_arrive(bars + B_WFREE);
                wg_fence();
#pragma unroll
                for (int j = 0; j < 4; j++) mma64_rs<1>(ya, af[4 * j], af[4 * j + 1], af[4 * j + 2], af[4 * j + 3], dF + j * 128, j);
                wg_commit();
#pragma unroll
                for (int j = 0; j < 4; j++) mma64_rs<1>(yb, ag[4 * j], ag[4 * j + 1], ag[4 * j + 2], ag[4 * j + 3], dF + j * 128, j);
                wg_commit();
                STAMP3(33);
                {
                    const uint32_t a0 = buf + (mi & 1) * 4096 + (16 * w + 8 * (mi >> 1) + gl) * 64 + ((gl >> 1) << 4);
#pragma unroll
                    for (int h = 0; h < 2; h++) {
                        if (h == 0) { wg_wait<1>(); pin(ya); pinu(af); STAMP3(34); } else { wg_wait<0>(); pin(yb); pinu(ag); }
                        const float(&yy)[32] = h ? yb : ya;
#pragma unroll
                        for (int c = 0; c < 4; c++) {
                            const int i = 8 * ((c + 2 * h) & 3), k = 8 * ((c + 2 * h + 1) & 3) + 2;
                            c2 x = {cmulc({yy[i], yy[i + 1]}, T[2 * c]), cmulc({yy[k], yy[k + 1]}, T[2 * c])};
                            fin<1>(x);
                            c2 y = {cmulc({yy[i + 4], yy[i + 5]}, T[2 * c + 1]), cmulc({yy[k + 4], yy[k + 5]}, T[2 * c + 1])};
                            fin<1>(y);
                            stsm4((a0 ^ (c << 4)) + h * 8192, pk(x.a.x, y.a.x), pk(x.b.x, y.b.x), pk(x.a.y, y.a.y), pk(x.b.y, y.b.y));
                        }
                    }
                }
                STAMP3(38);
                fence_async_sm();
                bar_sync(3, 128);
                wg_fence();
#pragma unroll
                for (int j = 0; j < 4; j++) mma128_ss<0, 1, 1>(vv, dF + j * 128, dB + j * 64, j);
                wg_commit();
                STAMP3(35);
                const int lane = fresh_lane(), g = lane >> 2, q = lane & 3;
                vp = padd(g_X + (4 << 20) + w * (8 * 32768) + (role ? u : 1) * 16384 + slot * 64,
                                         (g >> 1) * 32768 + (role ? g & 1 : u) * 32 + (((q ^ (slot >> 1)) & 1) << 4) + (q >> 1) * 8);
                const uint32_t tmask = (((g & 1) == ((slot >> 3) & 1) || !role) && q == ((slot >> 1) & 2)) ? ~1u : ~0u, tbit = (ep ^ (role + u ? 0 : g)) & ~tmask;
                be1 = twid(kap1 + 512 * q, 2048); be2 = csq(be1); be3 = cmul(be1, be2);
                asm volatile("pmevent 1;" : "+f"(be1.x), "+f"(be1.y), "+f"(be2.x), "+f"(be2.y), "+f"(be3.x), "+f"(be3.y), "+l"(vp)::"memory");
                wg_wait<0>();
                pin(vv);
                STAMP3(36);
#pragma unroll
                for (int k = 0; k < 16; k++) {
                    const int i = 8 * (k >> 1) + 2 * (k & 1);
                    vo[2 * k] = (pk(vv[i], vv[i + 1]) & tmask) | tbit;
                    vo[2 * k + 1] = pk(vv[i + 4], vv[i + 5]);
                }
                pinu(vo);
            }
            if (!role) mbar_wait(bars + B_IN + 16, 0);
            warp_arrive(bars + B_STG);
            const bool odd = fresh_lane() & 4;
            store_v<0, 4>(vo, vp, role || !odd);
            asm volatile("@p0 red.relaxed.gpu.global.add.u32 [%0], 1;" ::"l"(g_cnt + 32 + nu * 32) : "memory");
            store_v<4, 16>(vo, vp, role || odd);
            if (!spare) bar_arrive(9, 256);
        }
        if (spare) return;
        }
        {
            constexpr int Y = YP3;
            uint32_t sp[8];
            cf tw[8];
            if (hf) __nanosleep(400);
            ldtab<2, 2048>(sp, TAB_SP + fb * 4096 + t7 * 16);
            ldtab_cf<16>(tw, TAB_TW3 + fb * 2048 + (t7 >> 2) * 64);
            const uint64_t dF = opaque(mkdesc(sb + OFF_F, 16, 1024, 1)), dB = opaque(mkdesc(sb + OFF_P + hf * 8192, 1024, 256, 3));
            const uint8_t* op = padd(p.out + (1024 + fb) * 2048 + fcb * 32 + hf * 16, (t7 >> 2) * 32768 + (q >> 1) * 16 + (q & 1) * 32);
            float acc[64], out[64];
            mbar_wait(bars + B_IN + 16, 0);
            mbar_wait(bars + B_FG, 1);
            pinu(sp);
            wg_fence();
#pragma unroll
            for (int j = 0; j < 4; j++) {
                if (j == 2) {
                    wg_commit();
                    mbar_wait(bars + B_IN + 24, 0);
                    if (!hf) __nanosleep(200);
                    STAMP(25);
                    wg_fence();
                }
                const uint64_t db = dB + (j >> 1) * 1024 + (j & 1) * 32;
                mma112_ss(acc, dF + j * 2, db + 64, j);
                if (j & 1) mma16_rs(acc, 0u, sp[2 * j], 0u, sp[2 * j + 1], db, 1);
                else mma16_rs(acc, sp[2 * j], 0u, sp[2 * j + 1], 0u, db, j);
            }
            wg_commit();
            wg_wait<0>();
            pin(acc);
            pinu(sp);
            warp_arrive(bars + B_P3M);
            if (!hf) bar_sync(5, 256);
#pragma unroll
            for (int cl = 0; cl < 2; cl++) {
                c2 z[8];
#pragma unroll
                for (int n = 0; n < 8; n++) {
                    const int i = 4 * (2 * n + cl);
                    z[n] = {{acc[i], acc[i + 2]}, {acc[i + 1], acc[i + 3]}};
                }
                z[0] = {{z[0].a.x + z[0].a.y, z[0].a.x - z[0].a.y}, {z[0].b.x + z[0].b.y, z[0].b.x - z[0].b.y}};
                z[4] = mul2(z[4], tw[4]);
                fin<Y>(z[0], z[4]);
#pragma unroll
                for (int n = 1; n < 4; n++) {
                    const cf iw = n == 1 ? cf{0.38268343236508977f, 0.92387953251128674f}
                                         : (n == 2 ? cf{0.70710678118654752f, 0.70710678118654752f} : cf{0.92387953251128674f, 0.38268343236508977f});
                    c2 y = mul2(z[n], tw[n]);
                    fin<Y>(y);
                    const cf t = {tw[8 - n].x, -tw[8 - n].y};
                    c2 E = fma2(c2{{z[8 - n].a.x, -z[8 - n].a.y}, {z[8 - n].b.x, -z[8 - n].b.y}}, t, y);
                    fin<Y>(E);
                    z[n] = fma2(twm2(y, E), iw, E);
                    fin<Y>(z[n]);
                    z[8 - n] = {{fmaf(2.f, E.a.x, -z[n].a.x), fmaf(-2.f, E.a.y, z[n].a.y)}, {fmaf(2.f, E.b.x, -z[n].b.x), fmaf(-2.f, E.b.y, z[n].b.y)}};
                }
                dft8<false, Y>(z, tw);
#pragma unroll
                for (int m = 0; m < 8; m++) {
                    out[8 * m + 2 * cl] = z[m].a.x; out[8 * m + 2 * cl + 1] = z[m].b.x;
                    out[8 * m + 4 + 2 * cl] = z[m].a.y; out[8 * m + 5 + 2 * cl] = z[m].b.y;
                }
            }
            pin(out);
            if (hf) bar_arrive(5, 256);
            if (hf) STAMP(26);
#pragma unroll
            for (int m = 0; m < 16; m++) {
                asm volatile("st.global.v4.f32 [%0], {%1,%2,%3,%4};" ::"l"(op + (m - 8) * (1 << 20)), "f"(out[4 * m]), "f"(out[4 * m + 1]), "f"(out[4 * m + 2]), "f"(out[4 * m + 3]) : "memory");
                if (PACE_O && m < 15 && m % PACE_ON == PACE_ON - 1)
                    asm volatile("{.reg .pred p; mbarrier.test_wait.parity.shared::cta.b64 p, [%0], 0; @!p nanosleep.u32 %1;}" ::"r"(bars + B_DONE), "n"(PACE_O) : "memory");
            }
            STAMP(27);
        }
    }
}

typedef CUresult (*EncodeFn)(CUtensorMap*, CUtensorMapDataType, cuuint32_t, void*, const cuuint64_t*, const cuuint64_t*, const cuuint32_t*,
                             const cuuint32_t*, CUtensorMapInterleave, CUtensorMapSwizzle, CUtensorMapL2promotion, CUtensorMapFloatOOBfill);

static CUtensorMap make_map(EncodeFn enc, const void* ptr, int rank, const cuuint64_t* dims, const cuuint64_t* strides, const cuuint32_t* box,
                            CUtensorMapSwizzle swz, CUtensorMapL2promotion promo, CUtensorMapDataType dt = CU_TENSOR_MAP_DATA_TYPE_BFLOAT16) {
    CUtensorMap m;
    const cuuint32_t es[5] = {1, 1, 1, 1, 1};
    enc(&m, dt, rank, const_cast<void*>(ptr), dims, strides, box, es, CU_TENSOR_MAP_INTERLEAVE_NONE, swz, promo,
        CU_TENSOR_MAP_FLOAT_OOB_FILL_NONE);
    return m;
}

extern "C" void kernel_launch(void* const* d_in, const int* in_sizes, int n_in, void* d_out, int out_size) {
    void* fn = nullptr;
    cudaDriverEntryPointQueryResult qr;
    cudaGetDriverEntryPoint("cuTensorMapEncodeTiled", &fn, cudaEnableDefault, &qr);
    EncodeFn enc = (EncodeFn)fn;
    void* pX;
    cudaGetSymbolAddress(&pX, g_X);
    const CUtensorMapL2promotion P256 = CU_TENSOR_MAP_L2_PROMOTION_L2_256B, P0 = CU_TENSOR_MAP_L2_PROMOTION_NONE;

    const cuuint64_t dX[5] = {1024, 2, 4, 16, 16}, sX[4] = {2048, 32 * 2048, 2 * 2048, 128 * 2048};
    const cuuint32_t bX[5] = {64, 2, 4, 16, 1};
    CUtensorMap tmX = make_map(enc, d_in[3], 5, dX, sX, bX, CU_TENSOR_MAP_SWIZZLE_128B, P256);
    const cuuint64_t dXd[4] = {64, 2048, 2, 16}, sXd[3] = {2048, 64 * 2048, 128};
    const cuuint32_t bXd[4] = {64, 16, 2, 2};
    CUtensorMap tmXd = make_map(enc, d_in[3], 4, dXd, sXd, bXd, CU_TENSOR_MAP_SWIZZLE_128B, P256);
    const cuuint64_t dB[4] = {1024, 8, 4, 32}, sB[3] = {2048, 256 * 2048, 8 * 2048};
    const cuuint32_t bB4[4] = {64, 8, 2, 4};
    CUtensorMap tmBre = make_map(enc, d_in[6], 4, dB, sB, bB4, CU_TENSOR_MAP_SWIZZLE_128B, P256);
    CUtensorMap tmBim = make_map(enc, d_in[7], 4, dB, sB, bB4, CU_TENSOR_MAP_SWIZZLE_128B, P256);
    const cuuint64_t dC[5] = {1024, 2, 4, 2, 64}, sC[4] = {2048, 4 * 2048, 2 * 2048, 16 * 2048};
    const cuuint32_t bC[5] = {64, 2, 4, 2, 4};
    CUtensorMap tmCre = make_map(enc, d_in[8], 5, dC, sC, bC, CU_TENSOR_MAP_SWIZZLE_128B, P256);
    CUtensorMap tmCim = make_map(enc, d_in[9], 5, dC, sC, bC, CU_TENSOR_MAP_SWIZZLE_128B, P256);

    const cuuint64_t dU[2] = {8192, 256}, sU[1] = {16384};
    const cuuint32_t bU[2] = {64, 64};
    CUtensorMap tmUst = make_map(enc, pX, 2, dU, sU, bU, CU_TENSOR_MAP_SWIZZLE_128B, P0);
    const cuuint64_t dV[2] = {16384, 128}, sV[1] = {32768};
    const cuuint32_t bV[2] = {32, 128};
    CUtensorMap tmVst = make_map(enc, (uint8_t*)pX + (4 << 20), 2, dV, sV, bV, CU_TENSOR_MAP_SWIZZLE_NONE, P0);
    const cuuint64_t dF[2] = {512 * 1026 / 8, 4}, sF[1] = {512 * 1026};
    const cuuint32_t bF[2] = {WPITCH / 8, 4};
    CUtensorMap tmWr = make_map(enc, d_in[1], 2, dF, sF, bF, CU_TENSOR_MAP_SWIZZLE_NONE, P0, CU_TENSOR_MAP_DATA_TYPE_UINT64);
    CUtensorMap tmWi = make_map(enc, d_in[2], 2, dF, sF, bF, CU_TENSOR_MAP_SWIZZLE_NONE, P0, CU_TENSOR_MAP_DATA_TYPE_UINT64);

    const cuuint64_t dA[3] = {1024, 64, 32}, sA[2] = {32 * 2048, 2048};
    const cuuint32_t bA[3] = {32, 64, 1};
    CUtensorMap tmXa = make_map(enc, d_in[0], 3, dA, sA, bA, CU_TENSOR_MAP_SWIZZLE_64B, CU_TENSOR_MAP_L2_PROMOTION_L2_128B);

    Params p;
    p.wr = (const __nv_bfloat16*)d_in[1];
    p.wi = (const __nv_bfloat16*)d_in[2];
    p.lre = (const __nv_bfloat16*)d_in[4];
    p.lim = (const __nv_bfloat16*)d_in[5];
    p.ldt = (const __nv_bfloat16*)d_in[10];
    p.dsk = (const __nv_bfloat16*)d_in[11];
    p.out = (float*)d_out;
    int dev = 0, sms = 0;
    cudaGetDevice(&dev);
    cudaDeviceGetAttribute(&sms, cudaDevAttrMultiProcessorCount, dev);
    auto kernel = sms == 132 ? fused_kernel<true> : fused_kernel<false>;
    cudaFuncSetAttribute(kernel, cudaFuncAttributeMaxDynamicSharedMemorySize, SMEM_BYTES);
    kernel<<<132, 512, SMEM_BYTES>>>(tmX, tmBre, tmBim, tmCre, tmCim, tmXd, tmUst, tmVst, tmWr, tmWi, tmXa, p);
}
```
